```python
import torch

def _softmax(x, axis=-1):
    return torch.softmax(x, dim=axis)

def _gelu(x):
    return torch.nn.functional.gelu(x, approximate='tanh')

def _silu(x):
    return torch.nn.functional.silu(x)

def _sigmoid(x):
    return torch.sigmoid(x)

def _layernorm(x, axis=-1, eps=1e-05):
    m = x.mean(dim=axis, keepdim=True)
    v = x.var(dim=axis, keepdim=True, unbiased=False)
    return (x - m) / torch.sqrt(v + eps)

def _scatter_add(tgt, idx, src, axis=0):
    return tgt.clone().index_add_(axis, idx, src)

def _segment_sum(src, seg, n):
    out = torch.zeros((n,) + src.shape[1:], dtype=src.dtype)
    return out.index_add_(0, seg, src)

def _pad(x, pw):
    flat = tuple((v for pair in reversed(pw) for v in pair))
    return torch.nn.functional.pad(x, flat)
kernel_name = 'adaLN_cond__spectral_gfnet__mixer_token_mlp__prompt'

def setup_inputs():

    _w = lambda a: (lambda t: t.to(torch.bfloat16) if t.is_floating_point() else t)(torch.as_tensor(a))

    def _A_setup():
        B, S, D = (1, 2048, 576)
        Df = D // 2 + 1
        return {'x': _w((lambda *s: torch.randn(*s, dtype=torch.bfloat16) * 0.05)(B, S, D)), 'w_r': _w((lambda *s: torch.randn(*s, dtype=torch.bfloat16) * 1.6)(S, Df) * 0.02), 'w_i': _w((lambda *s: torch.randn(*s, dtype=torch.bfloat16) * 1.6)(S, Df) * 0.02)}
    _A_in = _A_setup()

    def _B_setup():
        B, S, D, F = (1, 2048, 576, 4608)
        return {'x': _w((lambda *s: torch.randn(*s, dtype=torch.bfloat16) * 0.05)(B, S, D)), 'w1': _w((lambda *s: torch.randn(*s, dtype=torch.bfloat16) * 0.8)(S, F) * S ** (-0.5)), 'b1': _w((lambda *s: torch.randn(*s, dtype=torch.bfloat16) * 12.8)(F) * 0.02), 'w2': _w((lambda *s: torch.randn(*s, dtype=torch.bfloat16) * 0.2)(F, S) * F ** (-0.5)), 'b2': _w((lambda *s: torch.randn(*s, dtype=torch.bfloat16) * 1.6)(S) * 0.02)}
    _B_in = _B_setup()
    return {'A_x': _A_in['x'], 'A_w_r': _A_in['w_r'], 'A_w_i': _A_in['w_i'], 'B_x': _B_in['x'], 'B_w1': _B_in['w1'], 'B_b1': _B_in['b1'], 'B_w2': _B_in['w2'], 'B_b2': _B_in['b2'], 'c': _w((lambda *s: torch.randn(*s, dtype=torch.bfloat16) * 0.1)(1, 576) * 8.0), 'w_mod': _w((lambda *s: torch.randn(*s, dtype=torch.bfloat16) * 0.1)(576, 6 * 576) * 576 ** (-0.5) * 8.0)}

def reference(A_x, A_w_r, A_w_i, B_x, B_w1, B_b1, B_w2, B_b2, c, w_mod):

    def _A_ref(x, w_r, w_i):
        B, S, D = x.shape
        X = (lambda x, axes=(-2, -1): torch.fft.rfft2(x.float(), dim=axes))(x, axes=(-2, -1))
        W = w_r + 1j * w_i
        X = X * W
        y = (lambda x, s, axes=(-2, -1): torch.fft.irfft2(x, s=s, dim=axes).to(torch.bfloat16))(X, (S, D), axes=(-2, -1))
        return y

    def _B_ref(x, w1, b1, w2, b2):
        B, S, D = x.shape
        h = _layernorm(x, axis=-1)
        u = torch.einsum('bsd,sf->bdf', h, w1) + b1
        u = _gelu(u)
        y = torch.einsum('bdf,fs->bds', u, w2) + b2
        return (lambda x, *d: x.permute(*d))(y, 0, 2, 1)
    x = A_x
    mod = (_silu(c) @ w_mod).reshape(c.shape[0], 6, 1, -1)
    sa, ca, ga, sb, cb, gb = (mod[:, 0].clone(), mod[:, 1].clone(), mod[:, 2].clone(), mod[:, 3].clone(), mod[:, 4].clone(), mod[:, 5].clone())
    h = _layernorm(x, axis=-1) * (1 + ca) + sa
    x = x + ga * _A_ref(h, A_w_r, A_w_i)
    h = _layernorm(x, axis=-1) * (1 + cb) + sb
    x = x + gb * _B_ref(h, B_w1, B_b1, B_w2, B_b2)
    return x
```

```cpp
#include <cuda_runtime.h>
#include <cuda_bf16.h>
#include <cuda.h>
#include <stdint.h>

namespace {

constexpr int S_ = 2048, D_ = 576, DF_ = 289, F_ = 4608;
constexpr int NCTA = 132, NTHR = 384;
constexpr int STAGE = 36864, NST = 6;
constexpr int FS = 4 * STAGE;
constexpr int FS_G = FS, FS_B = FS + 16384, FS_Y = FS + 40960;
constexpr int SMEM_BYTES = NST * STAGE + 1024;
#define KXV 32
constexpr int KX = KXV;

__device__ __align__(128) const uint32_t T_F64[4096] = {
0x3f803f80,0x0,0x3f803f80,0x0,0x3f803f80,0x0,0x3f803f80,0x0,0x3f803f80,0x0,0x3f803f80,0x0,
0x3f803f80,0x0,0x3f803f80,0x0,0x3f7f3f80,0xbdc90000,0x3f223f35,0xbf46bf35,0x3f753f7b,0xbe95be48,0x3ef13f0e,0xbf62bf55,
0x3f623f6d,0xbef1bec4,0x3e953ec4,0xbf75bf6d,0x3f463f55,0xbf22bf0e,0x3dc93e48,0xbf7fbf7b,0x3f7b3f80,0xbe480000,0xbe480000,0xbf7bbf80,
0x3f553f6d,0xbf0ebec4,0xbf0ebec4,0xbf55bf6d,0x3f0e3f35,0xbf55bf35,0xbf55bf35,0xbf0ebf35,0x3e483ec4,0xbf7bbf6d,0xbf7bbf6d,0xbe48bec4,
0x3f753f80,0xbe950000,0xbf62bf35,0xbef1bf35,0x3f223f55,0xbf46bf0e,0xbf7fbf7b,0x3dc9be48,0x3dc93ec4,0xbf7fbf6d,0xbf46bf6d,0x3f223ec4,
0xbef1be48,0xbf62bf7b,0xbe95bf0e,0x3f753f55,0x3f6d3f80,0xbec40000,0xbf6dbf80,0x3ec40000,0x3ec43f35,0xbf6dbf35,0xbec4bf35,0x3f6d3f35,
0xbec40000,0xbf6dbf80,0x3ec40000,0x3f6d3f80,0xbf6dbf35,0xbec4bf35,0x3f6d3f35,0x3ec43f35,0x3f623f80,0xbef10000,0xbe95bf35,0x3f753f35,
0x3dc93f0e,0xbf7fbf55,0x3f223e48,0x3f463f7b,0xbf46bec4,0xbf22bf6d,0x3f7f3f6d,0xbdc93ec4,0xbf75bf7b,0x3e95be48,0x3ef13f55,0xbf62bf0e,
0x3f553f80,0xbf0e0000,0x3f0e0000,0x3f553f80,0xbe483ec4,0xbf7bbf6d,0x3f7b3f6d,0xbe483ec4,0xbf7bbf35,0xbe48bf35,0x3e483f35,0xbf7bbf35,
0xbf0ebf6d,0x3f553ec4,0xbf55bec4,0xbf0ebf6d,0x3f463f80,0xbf220000,0x3f7f3f35,0x3dc93f35,0xbef13e48,0xbf62bf7b,0x3e953f55,0xbf75bf0e,
0xbf75bf6d,0x3e95bec4,0xbf62bec4,0xbef1bf6d,0x3dc9bf0e,0x3f7f3f55,0xbf22bf7b,0x3f463e48,0x3f353f80,0xbf350000,0x3f353f80,0xbf350000,
0xbf350000,0xbf35bf80,0xbf350000,0xbf35bf80,0xbf35bf80,0x3f350000,0xbf35bf80,0x3f350000,0x3f350000,0x3f353f80,0x3f350000,0x3f353f80,
0x3f223f80,0xbf460000,0xbdc93f35,0xbf7fbf35,0xbf62be48,0xbef1bf7b,0xbf75bf55,0x3e95bf0e,0xbe95bf6d,0x3f753ec4,0x3ef1bec4,0x3f623f6d,
0x3f7f3f0e,0x3dc93f55,0x3f463f7b,0xbf223e48,0x3f0e3f80,0xbf550000,0xbf550000,0xbf0ebf80,0xbf7bbec4,0xbe48bf6d,0xbe48bf6d,0x3f7b3ec4,
0x3e48bf35,0x3f7b3f35,0x3f7b3f35,0xbe483f35,0x3f553f6d,0xbf0e3ec4,0xbf0e3ec4,0xbf55bf6d,0x3ef13f80,0xbf620000,0xbf75bf35,0x3e95bf35,
0xbf7fbf0e,0x3dc9bf55,0x3f46be48,0x3f223f7b,0x3f22bec4,0x3f463f6d,0x3dc93f6d,0xbf7fbec4,0x3e953f7b,0xbf75be48,0xbf62bf55,0x3ef1bf0e,
0x3ec43f80,0xbf6d0000,0xbec4bf80,0x3f6d0000,0xbf6dbf35,0x3ec4bf35,0x3f6d3f35,0xbec43f35,0x3f6d0000,0x3ec43f80,0xbf6d0000,0xbec4bf80,
0xbec43f35,0xbf6dbf35,0x3ec4bf35,0x3f6d3f35,0x3e953f80,0xbf750000,0x3ef1bf35,0x3f623f35,0xbf46bf55,0x3f22bf0e,0x3dc93f7b,0xbf7fbe48,
0x3f7f3ec4,0xbdc93f6d,0xbf22bf6d,0x3f46bec4,0xbf623e48,0xbef1bf7b,0x3f753f0e,0xbe953f55,0x3e483f80,0xbf7b0000,0x3f7b0000,0x3e483f80,
0xbf0ebf6d,0x3f55bec4,0xbf553ec4,0xbf0ebf6d,0x3f553f35,0xbf0e3f35,0x3f0ebf35,0x3f553f35,0xbf7bbec4,0x3e48bf6d,0xbe483f6d,0xbf7bbec4,
0x3dc93f80,0xbf7f0000,0x3f463f35,0xbf223f35,0xbe95bf7b,0x3f75be48,0xbf62bf0e,0x3ef1bf55,0x3ef13f6d,0xbf623ec4,0x3f753ec4,0xbe953f6d,
0xbf22bf55,0x3f46bf0e,0xbf7fbe48,0x3dc9bf7b,0x3f80,0xbf800000,0x3f80,0xbf800000,0xbf80,0x3f800000,0xbf80,0x3f800000,
0x3f80,0xbf800000,0x3f80,0xbf800000,0xbf80,0x3f800000,0xbf80,0x3f800000,0xbdc93f80,0xbf7f0000,0xbf463f35,0xbf22bf35,
0x3e95bf7b,0x3f753e48,0x3f62bf0e,0x3ef13f55,0xbef13f6d,0xbf62bec4,0xbf753ec4,0xbe95bf6d,0x3f22bf55,0x3f463f0e,0x3f7fbe48,0x3dc93f7b,
0xbe483f80,0xbf7b0000,0xbf7b0000,0x3e48bf80,0x3f0ebf6d,0x3f553ec4,0x3f553ec4,0xbf0e3f6d,0xbf553f35,0xbf0ebf35,0xbf0ebf35,0x3f55bf35,
0x3f7bbec4,0x3e483f6d,0x3e483f6d,0xbf7b3ec4,0xbe953f80,0xbf750000,0xbef1bf35,0x3f62bf35,0x3f46bf55,0x3f223f0e,0xbdc93f7b,0xbf7f3e48,
0xbf7f3ec4,0xbdc9bf6d,0x3f22bf6d,0x3f463ec4,0x3f623e48,0xbef13f7b,0xbf753f0e,0xbe95bf55,0xbec43f80,0xbf6d0000,0x3ec4bf80,0x3f6d0000,
0x3f6dbf35,0x3ec43f35,0xbf6d3f35,0xbec4bf35,0xbf6d0000,0x3ec4bf80,0x3f6d0000,0xbec43f80,0x3ec43f35,0xbf6d3f35,0xbec4bf35,0x3f6dbf35,
0xbef13f80,0xbf620000,0x3f75bf35,0x3e953f35,0x3f7fbf0e,0x3dc93f55,0xbf46be48,0x3f22bf7b,0xbf22bec4,0x3f46bf6d,0xbdc93f6d,0xbf7f3ec4,
0xbe953f7b,0xbf753e48,0x3f62bf55,0x3ef13f0e,0xbf0e3f80,0xbf550000,0x3f550000,0xbf0e3f80,0x3f7bbec4,0xbe483f6d,0x3e48bf6d,0x3f7bbec4,
0xbe48bf35,0x3f7bbf35,0xbf7b3f35,0xbe48bf35,0xbf553f6d,0xbf0ebec4,0x3f0e3ec4,0xbf553f6d,0xbf223f80,0xbf460000,0x3dc93f35,0xbf7f3f35,
0x3f62be48,0xbef13f7b,0x3f75bf55,0x3e953f0e,0x3e95bf6d,0x3f75bec4,0xbef1bec4,0x3f62bf6d,0xbf7f3f0e,0x3dc9bf55,0xbf463f7b,0xbf22be48,
0xbf353f80,0xbf350000,0xbf353f80,0xbf350000,0x3f350000,0xbf353f80,0x3f350000,0xbf353f80,0x3f35bf80,0x3f350000,0x3f35bf80,0x3f350000,
0xbf350000,0x3f35bf80,0xbf350000,0x3f35bf80,0xbf463f80,0xbf220000,0xbf7f3f35,0x3dc9bf35,0x3ef13e48,0xbf623f7b,0xbe953f55,0xbf753f0e,
0x3f75bf6d,0x3e953ec4,0x3f62bec4,0xbef13f6d,0xbdc9bf0e,0x3f7fbf55,0x3f22bf7b,0x3f46be48,0xbf553f80,0xbf0e0000,0xbf0e0000,0x3f55bf80,
0x3e483ec4,0xbf7b3f6d,0xbf7b3f6d,0xbe48bec4,0x3f7bbf35,0xbe483f35,0xbe483f35,0xbf7b3f35,0x3f0ebf6d,0x3f55bec4,0x3f55bec4,0xbf0e3f6d,
0xbf623f80,0xbef10000,0x3e95bf35,0x3f75bf35,0xbdc93f0e,0xbf7f3f55,0xbf223e48,0x3f46bf7b,0x3f46bec4,0xbf223f6d,0xbf7f3f6d,0xbdc9bec4,
0x3f75bf7b,0x3e953e48,0xbef13f55,0xbf623f0e,0xbf6d3f80,0xbec40000,0x3f6dbf80,0x3ec40000,0xbec43f35,0xbf6d3f35,0x3ec4bf35,0x3f6dbf35,
0x3ec40000,0xbf6d3f80,0xbec40000,0x3f6dbf80,0x3f6dbf35,0xbec43f35,0xbf6d3f35,0x3ec4bf35,0xbf753f80,0xbe950000,0x3f62bf35,0xbef13f35,
0xbf223f55,0xbf463f0e,0x3f7fbf7b,0x3dc93e48,0xbdc93ec4,0xbf7f3f6d,0x3f46bf6d,0x3f22bec4,0x3ef1be48,0xbf623f7b,0x3e95bf0e,0x3f75bf55,
0xbf7b3f80,0xbe480000,0x3e480000,0xbf7b3f80,0xbf553f6d,0xbf0e3ec4,0x3f0ebec4,0xbf553f6d,0xbf0e3f35,0xbf553f35,0x3f55bf35,0xbf0e3f35,
0xbe483ec4,0xbf7b3f6d,0x3f7bbf6d,0xbe483ec4,0xbf7f3f80,0xbdc90000,0xbf223f35,0xbf463f35,0xbf753f7b,0xbe953e48,0xbef13f0e,0xbf623f55,
0xbf623f6d,0xbef13ec4,0xbe953ec4,0xbf753f6d,0xbf463f55,0xbf223f0e,0xbdc93e48,0xbf7f3f7b,0x3f803f80,0x0,0x3f803f80,0x0,
0x3f803f80,0x0,0x3f803f80,0x0,0x3f803f80,0x0,0x3f803f80,0x0,0x3f803f80,0x0,0x3f803f80,0x0,
0xbdc90000,0xbf7fbf80,0xbf46bf35,0xbf22bf35,0xbe95be48,0xbf75bf7b,0xbf62bf55,0xbef1bf0e,0xbef1bec4,0xbf62bf6d,0xbf75bf6d,0xbe95bec4,
0xbf22bf0e,0xbf46bf55,0xbf7fbf7b,0xbdc9be48,0xbf7bbf80,0x3e480000,0x3e480000,0x3f7b3f80,0xbf55bf6d,0x3f0e3ec4,0x3f0e3ec4,0x3f553f6d,
0xbf0ebf35,0x3f553f35,0x3f553f35,0x3f0e3f35,0xbe48bec4,0x3f7b3f6d,0x3f7b3f6d,0x3e483ec4,0x3e950000,0x3f753f80,0x3ef13f35,0xbf62bf35,
0x3f463f0e,0x3f223f55,0xbdc93e48,0xbf7fbf7b,0x3f7f3f6d,0x3dc93ec4,0xbf22bec4,0xbf46bf6d,0x3f623f7b,0xbef1be48,0xbf75bf55,0xbe95bf0e,
0x3f6d3f80,0xbec40000,0xbf6dbf80,0x3ec40000,0x3ec43f35,0xbf6dbf35,0xbec4bf35,0x3f6d3f35,0xbec40000,0xbf6dbf80,0x3ec40000,0x3f6d3f80,
0xbf6dbf35,0xbec4bf35,0x3f6d3f35,0x3ec43f35,0xbef10000,0xbf62bf80,0x3f753f35,0x3e953f35,0xbf7fbf55,0xbdc9bf0e,0x3f463f7b,0xbf22be48,
0xbf22bf6d,0x3f463ec4,0xbdc93ec4,0xbf7fbf6d,0x3e95be48,0x3f753f7b,0xbf62bf0e,0xbef1bf55,0xbf55bf80,0x3f0e0000,0xbf0e0000,0xbf55bf80,
0x3e48bec4,0x3f7b3f6d,0xbf7bbf6d,0x3e48bec4,0x3f7b3f35,0x3e483f35,0xbe48bf35,0x3f7b3f35,0x3f0e3f6d,0xbf55bec4,0x3f553ec4,0x3f0e3f6d,
0x3f220000,0x3f463f80,0xbdc9bf35,0x3f7f3f35,0x3f623f7b,0xbef13e48,0x3f753f0e,0x3e953f55,0xbe953ec4,0xbf75bf6d,0x3ef13f6d,0xbf62bec4,
0xbf7fbf55,0x3dc9bf0e,0xbf46be48,0xbf22bf7b,0x3f353f80,0xbf350000,0x3f353f80,0xbf350000,0xbf350000,0xbf35bf80,0xbf350000,0xbf35bf80,
0xbf35bf80,0x3f350000,0xbf35bf80,0x3f350000,0x3f350000,0x3f353f80,0x3f350000,0x3f353f80,0xbf460000,0xbf22bf80,0xbf7fbf35,0x3dc9bf35,
0xbef1bf7b,0x3f623e48,0x3e95bf0e,0x3f753f55,0x3f753ec4,0x3e953f6d,0x3f623f6d,0xbef13ec4,0x3dc93f55,0xbf7fbf0e,0xbf223e48,0xbf46bf7b,
0xbf0ebf80,0x3f550000,0x3f550000,0x3f0e3f80,0x3f7b3ec4,0x3e483f6d,0x3e483f6d,0xbf7bbec4,0xbe483f35,0xbf7bbf35,0xbf7bbf35,0x3e48bf35,
0xbf55bf6d,0x3f0ebec4,0x3f0ebec4,0x3f553f6d,0x3f620000,0x3ef13f80,0xbe953f35,0xbf75bf35,0xbdc93f55,0xbf7fbf0e,0xbf22bf7b,0x3f46be48,
0xbf46bf6d,0x3f22bec4,0x3f7f3ec4,0x3dc93f6d,0x3f753e48,0x3e953f7b,0xbef13f0e,0xbf62bf55,0x3ec43f80,0xbf6d0000,0xbec4bf80,0x3f6d0000,
0xbf6dbf35,0x3ec4bf35,0x3f6d3f35,0xbec43f35,0x3f6d0000,0x3ec43f80,0xbf6d0000,0xbec4bf80,0xbec43f35,0xbf6dbf35,0x3ec4bf35,0x3f6d3f35,
0xbf750000,0xbe95bf80,0x3f623f35,0xbef13f35,0x3f22bf0e,0x3f463f55,0xbf7fbe48,0xbdc9bf7b,0xbdc93f6d,0xbf7fbec4,0x3f46bec4,0x3f223f6d,
0xbef1bf7b,0x3f62be48,0xbe953f55,0xbf75bf0e,0xbe48bf80,0x3f7b0000,0xbf7b0000,0xbe48bf80,0x3f0e3f6d,0xbf553ec4,0x3f55bec4,0x3f0e3f6d,
0xbf55bf35,0x3f0ebf35,0xbf0e3f35,0xbf55bf35,0x3f7b3ec4,0xbe483f6d,0x3e48bf6d,0x3f7b3ec4,0x3f7f0000,0x3dc93f80,0x3f22bf35,0x3f463f35,
0xbf753e48,0xbe95bf7b,0xbef13f55,0xbf62bf0e,0x3f62bec4,0x3ef13f6d,0x3e95bf6d,0x3f753ec4,0xbf463f0e,0xbf22bf55,0xbdc93f7b,0xbf7fbe48,
0x3f80,0xbf800000,0x3f80,0xbf800000,0xbf80,0x3f800000,0xbf80,0x3f800000,0x3f80,0xbf800000,0x3f80,0xbf800000,
0xbf80,0x3f800000,0xbf80,0x3f800000,0xbf7f0000,0x3dc9bf80,0xbf22bf35,0x3f46bf35,0x3f753e48,0xbe953f7b,0x3ef13f55,0xbf623f0e,
0xbf62bec4,0x3ef1bf6d,0xbe95bf6d,0x3f75bec4,0x3f463f0e,0xbf223f55,0x3dc93f7b,0xbf7f3e48,0x3e48bf80,0x3f7b0000,0x3f7b0000,0xbe483f80,
0xbf0e3f6d,0xbf55bec4,0xbf55bec4,0x3f0ebf6d,0x3f55bf35,0x3f0e3f35,0x3f0e3f35,0xbf553f35,0xbf7b3ec4,0xbe48bf6d,0xbe48bf6d,0x3f7bbec4,
0x3f750000,0xbe953f80,0xbf623f35,0xbef1bf35,0xbf22bf0e,0x3f46bf55,0x3f7fbe48,0xbdc93f7b,0x3dc93f6d,0xbf7f3ec4,0xbf46bec4,0x3f22bf6d,
0x3ef1bf7b,0x3f623e48,0x3e953f55,0xbf753f0e,0xbec43f80,0xbf6d0000,0x3ec4bf80,0x3f6d0000,0x3f6dbf35,0x3ec43f35,0xbf6d3f35,0xbec4bf35,
0xbf6d0000,0x3ec4bf80,0x3f6d0000,0xbec43f80,0x3ec43f35,0xbf6d3f35,0xbec4bf35,0x3f6dbf35,0xbf620000,0x3ef1bf80,0x3e953f35,0xbf753f35,
0x3dc93f55,0xbf7f3f0e,0x3f22bf7b,0x3f463e48,0x3f46bf6d,0x3f223ec4,0xbf7f3ec4,0x3dc9bf6d,0xbf753e48,0x3e95bf7b,0x3ef13f0e,0xbf623f55,
0x3f0ebf80,0x3f550000,0xbf550000,0x3f0ebf80,0xbf7b3ec4,0x3e48bf6d,0xbe483f6d,0xbf7b3ec4,0x3e483f35,0xbf7b3f35,0x3f7bbf35,0x3e483f35,
0x3f55bf6d,0x3f0e3ec4,0xbf0ebec4,0x3f55bf6d,0x3f460000,0xbf223f80,0x3f7fbf35,0x3dc93f35,0x3ef1bf7b,0x3f62be48,0xbe95bf0e,0x3f75bf55,
0xbf753ec4,0x3e95bf6d,0xbf623f6d,0xbef1bec4,0xbdc93f55,0xbf7f3f0e,0x3f223e48,0xbf463f7b,0xbf353f80,0xbf350000,0xbf353f80,0xbf350000,
0x3f350000,0xbf353f80,0x3f350000,0xbf353f80,0x3f35bf80,0x3f350000,0x3f35bf80,0x3f350000,0xbf350000,0x3f35bf80,0xbf350000,0x3f35bf80,
0xbf220000,0x3f46bf80,0x3dc9bf35,0x3f7fbf35,0xbf623f7b,0xbef1be48,0xbf753f0e,0x3e95bf55,0x3e953ec4,0xbf753f6d,0xbef13f6d,0xbf623ec4,
0x3f7fbf55,0x3dc93f0e,0x3f46be48,0xbf223f7b,0x3f55bf80,0x3f0e0000,0x3f0e0000,0xbf553f80,0xbe48bec4,0x3f7bbf6d,0x3f7bbf6d,0x3e483ec4,
0xbf7b3f35,0x3e48bf35,0x3e48bf35,0x3f7bbf35,0xbf0e3f6d,0xbf553ec4,0xbf553ec4,0x3f0ebf6d,0x3ef10000,0xbf623f80,0xbf753f35,0x3e95bf35,
0x3f7fbf55,0xbdc93f0e,0xbf463f7b,0xbf223e48,0x3f22bf6d,0x3f46bec4,0x3dc93ec4,0xbf7f3f6d,0xbe95be48,0x3f75bf7b,0x3f62bf0e,0xbef13f55,
0xbf6d3f80,0xbec40000,0x3f6dbf80,0x3ec40000,0xbec43f35,0xbf6d3f35,0x3ec4bf35,0x3f6dbf35,0x3ec40000,0xbf6d3f80,0xbec40000,0x3f6dbf80,
0x3f6dbf35,0xbec43f35,0xbf6d3f35,0x3ec4bf35,0xbe950000,0x3f75bf80,0xbef13f35,0xbf623f35,0xbf463f0e,0x3f22bf55,0x3dc93e48,0xbf7f3f7b,
0xbf7f3f6d,0x3dc9bec4,0x3f22bec4,0xbf463f6d,0xbf623f7b,0xbef13e48,0x3f75bf55,0xbe953f0e,0x3f7bbf80,0x3e480000,0xbe480000,0x3f7bbf80,
0x3f55bf6d,0x3f0ebec4,0xbf0e3ec4,0x3f55bf6d,0x3f0ebf35,0x3f55bf35,0xbf553f35,0x3f0ebf35,0x3e48bec4,0x3f7bbf6d,0xbf7b3f6d,0x3e48bec4,
0x3dc90000,0xbf7f3f80,0x3f46bf35,0xbf223f35,0x3e95be48,0xbf753f7b,0x3f62bf55,0xbef13f0e,0x3ef1bec4,0xbf623f6d,0x3f75bf6d,0xbe953ec4,
0x3f22bf0e,0xbf463f55,0x3f7fbf7b,0xbdc93e48,0x3f803f80,0x0,0x3f803f80,0x0,0x3f803f80,0x0,0x3f803f80,0x0,
0x3f803f80,0x0,0x3f803f80,0x0,0x3f803f80,0x0,0x3f803f80,0x0,0xbf7fbf80,0x3dc90000,0xbf22bf35,0x3f463f35,
0xbf75bf7b,0x3e953e48,0xbef1bf0e,0x3f623f55,0xbf62bf6d,0x3ef13ec4,0xbe95bec4,0x3f753f6d,0xbf46bf55,0x3f223f0e,0xbdc9be48,0x3f7f3f7b,
0x3f7b3f80,0xbe480000,0xbe480000,0xbf7bbf80,0x3f553f6d,0xbf0ebec4,0xbf0ebec4,0xbf55bf6d,0x3f0e3f35,0xbf55bf35,0xbf55bf35,0xbf0ebf35,
0x3e483ec4,0xbf7bbf6d,0xbf7bbf6d,0xbe48bec4,0xbf75bf80,0x3e950000,0x3f623f35,0x3ef13f35,0xbf22bf55,0x3f463f0e,0x3f7f3f7b,0xbdc93e48,
0xbdc9bec4,0x3f7f3f6d,0x3f463f6d,0xbf22bec4,0x3ef13e48,0x3f623f7b,0x3e953f0e,0xbf75bf55,0x3f6d3f80,0xbec40000,0xbf6dbf80,0x3ec40000,
0x3ec43f35,0xbf6dbf35,0xbec4bf35,0x3f6d3f35,0xbec40000,0xbf6dbf80,0x3ec40000,0x3f6d3f80,0xbf6dbf35,0xbec4bf35,0x3f6d3f35,0x3ec43f35,
0xbf62bf80,0x3ef10000,0x3e953f35,0xbf75bf35,0xbdc9bf0e,0x3f7f3f55,0xbf22be48,0xbf46bf7b,0x3f463ec4,0x3f223f6d,0xbf7fbf6d,0x3dc9bec4,
0x3f753f7b,0xbe953e48,0xbef1bf55,0x3f623f0e,0x3f553f80,0xbf0e0000,0x3f0e0000,0x3f553f80,0xbe483ec4,0xbf7bbf6d,0x3f7b3f6d,0xbe483ec4,
0xbf7bbf35,0xbe48bf35,0x3e483f35,0xbf7bbf35,0xbf0ebf6d,0x3f553ec4,0xbf55bec4,0xbf0ebf6d,0xbf46bf80,0x3f220000,0xbf7fbf35,0xbdc9bf35,
0x3ef1be48,0x3f623f7b,0xbe95bf55,0x3f753f0e,0x3f753f6d,0xbe953ec4,0x3f623ec4,0x3ef13f6d,0xbdc93f0e,0xbf7fbf55,0x3f223f7b,0xbf46be48,
0x3f353f80,0xbf350000,0x3f353f80,0xbf350000,0xbf350000,0xbf35bf80,0xbf350000,0xbf35bf80,0xbf35bf80,0x3f350000,0xbf35bf80,0x3f350000,
0x3f350000,0x3f353f80,0x3f350000,0x3f353f80,0xbf22bf80,0x3f460000,0x3dc9bf35,0x3f7f3f35,0x3f623e48,0x3ef13f7b,0x3f753f55,0xbe953f0e,
0x3e953f6d,0xbf75bec4,0xbef13ec4,0xbf62bf6d,0xbf7fbf0e,0xbdc9bf55,0xbf46bf7b,0x3f22be48,0x3f0e3f80,0xbf550000,0xbf550000,0xbf0ebf80,
0xbf7bbec4,0xbe48bf6d,0xbe48bf6d,0x3f7b3ec4,0x3e48bf35,0x3f7b3f35,0x3f7b3f35,0xbe483f35,0x3f553f6d,0xbf0e3ec4,0xbf0e3ec4,0xbf55bf6d,
0xbef1bf80,0x3f620000,0x3f753f35,0xbe953f35,0x3f7f3f0e,0xbdc93f55,0xbf463e48,0xbf22bf7b,0xbf223ec4,0xbf46bf6d,0xbdc9bf6d,0x3f7f3ec4,
0xbe95bf7b,0x3f753e48,0x3f623f55,0xbef13f0e,0x3ec43f80,0xbf6d0000,0xbec4bf80,0x3f6d0000,0xbf6dbf35,0x3ec4bf35,0x3f6d3f35,0xbec43f35,
0x3f6d0000,0x3ec43f80,0xbf6d0000,0xbec4bf80,0xbec43f35,0xbf6dbf35,0x3ec4bf35,0x3f6d3f35,0xbe95bf80,0x3f750000,0xbef13f35,0xbf62bf35,
0x3f463f55,0xbf223f0e,0xbdc9bf7b,0x3f7f3e48,0xbf7fbec4,0x3dc9bf6d,0x3f223f6d,0xbf463ec4,0x3f62be48,0x3ef13f7b,0xbf75bf0e,0x3e95bf55,
0x3e483f80,0xbf7b0000,0x3f7b0000,0x3e483f80,0xbf0ebf6d,0x3f55bec4,0xbf553ec4,0xbf0ebf6d,0x3f553f35,0xbf0e3f35,0x3f0ebf35,0x3f553f35,
0xbf7bbec4,0x3e48bf6d,0xbe483f6d,0xbf7bbec4,0xbdc9bf80,0x3f7f0000,0xbf46bf35,0x3f22bf35,0x3e953f7b,0xbf753e48,0x3f623f0e,0xbef13f55,
0xbef1bf6d,0x3f62bec4,0xbf75bec4,0x3e95bf6d,0x3f223f55,0xbf463f0e,0x3f7f3e48,0xbdc93f7b,0x3f80,0xbf800000,0x3f80,0xbf800000,
0xbf80,0x3f800000,0xbf80,0x3f800000,0x3f80,0xbf800000,0x3f80,0xbf800000,0xbf80,0x3f800000,0xbf80,0x3f800000,
0x3dc9bf80,0x3f7f0000,0x3f46bf35,0x3f223f35,0xbe953f7b,0xbf75be48,0xbf623f0e,0xbef1bf55,0x3ef1bf6d,0x3f623ec4,0x3f75bec4,0x3e953f6d,
0xbf223f55,0xbf46bf0e,0xbf7f3e48,0xbdc9bf7b,0xbe483f80,0xbf7b0000,0xbf7b0000,0x3e48bf80,0x3f0ebf6d,0x3f553ec4,0x3f553ec4,0xbf0e3f6d,
0xbf553f35,0xbf0ebf35,0xbf0ebf35,0x3f55bf35,0x3f7bbec4,0x3e483f6d,0x3e483f6d,0xbf7b3ec4,0x3e95bf80,0x3f750000,0x3ef13f35,0xbf623f35,
0xbf463f55,0xbf22bf0e,0x3dc9bf7b,0x3f7fbe48,0x3f7fbec4,0x3dc93f6d,0xbf223f6d,0xbf46bec4,0xbf62be48,0x3ef1bf7b,0x3f75bf0e,0x3e953f55,
0xbec43f80,0xbf6d0000,0x3ec4bf80,0x3f6d0000,0x3f6dbf35,0x3ec43f35,0xbf6d3f35,0xbec4bf35,0xbf6d0000,0x3ec4bf80,0x3f6d0000,0xbec43f80,
0x3ec43f35,0xbf6d3f35,0xbec4bf35,0x3f6dbf35,0x3ef1bf80,0x3f620000,0xbf753f35,0xbe95bf35,0xbf7f3f0e,0xbdc9bf55,0x3f463e48,0xbf223f7b,
0x3f223ec4,0xbf463f6d,0x3dc9bf6d,0x3f7fbec4,0x3e95bf7b,0x3f75be48,0xbf623f55,0xbef1bf0e,0xbf0e3f80,0xbf550000,0x3f550000,0xbf0e3f80,
0x3f7bbec4,0xbe483f6d,0x3e48bf6d,0x3f7bbec4,0xbe48bf35,0x3f7bbf35,0xbf7b3f35,0xbe48bf35,0xbf553f6d,0xbf0ebec4,0x3f0e3ec4,0xbf553f6d,
0x3f22bf80,0x3f460000,0xbdc9bf35,0x3f7fbf35,0xbf623e48,0x3ef1bf7b,0xbf753f55,0xbe95bf0e,0xbe953f6d,0xbf753ec4,0x3ef13ec4,0xbf623f6d,
0x3f7fbf0e,0xbdc93f55,0x3f46bf7b,0x3f223e48,0xbf353f80,0xbf350000,0xbf353f80,0xbf350000,0x3f350000,0xbf353f80,0x3f350000,0xbf353f80,
0x3f35bf80,0x3f350000,0x3f35bf80,0x3f350000,0xbf350000,0x3f35bf80,0xbf350000,0x3f35bf80,0x3f46bf80,0x3f220000,0x3f7fbf35,0xbdc93f35,
0xbef1be48,0x3f62bf7b,0x3e95bf55,0x3f75bf0e,0xbf753f6d,0xbe95bec4,0xbf623ec4,0x3ef1bf6d,0x3dc93f0e,0xbf7f3f55,0xbf223f7b,0xbf463e48,
0xbf553f80,0xbf0e0000,0xbf0e0000,0x3f55bf80,0x3e483ec4,0xbf7b3f6d,0xbf7b3f6d,0xbe48bec4,0x3f7bbf35,0xbe483f35,0xbe483f35,0xbf7b3f35,
0x3f0ebf6d,0x3f55bec4,0x3f55bec4,0xbf0e3f6d,0x3f62bf80,0x3ef10000,0xbe953f35,0xbf753f35,0x3dc9bf0e,0x3f7fbf55,0x3f22be48,0xbf463f7b,
0xbf463ec4,0x3f22bf6d,0x3f7fbf6d,0x3dc93ec4,0xbf753f7b,0xbe95be48,0x3ef1bf55,0x3f62bf0e,0xbf6d3f80,0xbec40000,0x3f6dbf80,0x3ec40000,
0xbec43f35,0xbf6d3f35,0x3ec4bf35,0x3f6dbf35,0x3ec40000,0xbf6d3f80,0xbec40000,0x3f6dbf80,0x3f6dbf35,0xbec43f35,0xbf6d3f35,0x3ec4bf35,
0x3f75bf80,0x3e950000,0xbf623f35,0x3ef1bf35,0x3f22bf55,0x3f46bf0e,0xbf7f3f7b,0xbdc9be48,0x3dc9bec4,0x3f7fbf6d,0xbf463f6d,0xbf223ec4,
0xbef13e48,0x3f62bf7b,0xbe953f0e,0xbf753f55,0xbf7b3f80,0xbe480000,0x3e480000,0xbf7b3f80,0xbf553f6d,0xbf0e3ec4,0x3f0ebec4,0xbf553f6d,
0xbf0e3f35,0xbf553f35,0x3f55bf35,0xbf0e3f35,0xbe483ec4,0xbf7b3f6d,0x3f7bbf6d,0xbe483ec4,0x3f7fbf80,0x3dc90000,0x3f22bf35,0x3f46bf35,
0x3f75bf7b,0x3e95be48,0x3ef1bf0e,0x3f62bf55,0x3f62bf6d,0x3ef1bec4,0x3e95bec4,0x3f75bf6d,0x3f46bf55,0x3f22bf0e,0x3dc9be48,0x3f7fbf7b,
0x3f803f80,0x0,0x3f803f80,0x0,0x3f803f80,0x0,0x3f803f80,0x0,0x3f803f80,0x0,0x3f803f80,0x0,
0x3f803f80,0x0,0x3f803f80,0x0,0x3dc90000,0x3f7f3f80,0x3f463f35,0x3f223f35,0x3e953e48,0x3f753f7b,0x3f623f55,0x3ef13f0e,
0x3ef13ec4,0x3f623f6d,0x3f753f6d,0x3e953ec4,0x3f223f0e,0x3f463f55,0x3f7f3f7b,0x3dc93e48,0xbf7bbf80,0x3e480000,0x3e480000,0x3f7b3f80,
0xbf55bf6d,0x3f0e3ec4,0x3f0e3ec4,0x3f553f6d,0xbf0ebf35,0x3f553f35,0x3f553f35,0x3f0e3f35,0xbe48bec4,0x3f7b3f6d,0x3f7b3f6d,0x3e483ec4,
0xbe950000,0xbf75bf80,0xbef1bf35,0x3f623f35,0xbf46bf0e,0xbf22bf55,0x3dc9be48,0x3f7f3f7b,0xbf7fbf6d,0xbdc9bec4,0x3f223ec4,0x3f463f6d,
0xbf62bf7b,0x3ef13e48,0x3f753f55,0x3e953f0e,0x3f6d3f80,0xbec40000,0xbf6dbf80,0x3ec40000,0x3ec43f35,0xbf6dbf35,0xbec4bf35,0x3f6d3f35,
0xbec40000,0xbf6dbf80,0x3ec40000,0x3f6d3f80,0xbf6dbf35,0xbec4bf35,0x3f6d3f35,0x3ec43f35,0x3ef10000,0x3f623f80,0xbf75bf35,0xbe95bf35,
0x3f7f3f55,0x3dc93f0e,0xbf46bf7b,0x3f223e48,0x3f223f6d,0xbf46bec4,0x3dc9bec4,0x3f7f3f6d,0xbe953e48,0xbf75bf7b,0x3f623f0e,0x3ef13f55,
0xbf55bf80,0x3f0e0000,0xbf0e0000,0xbf55bf80,0x3e48bec4,0x3f7b3f6d,0xbf7bbf6d,0x3e48bec4,0x3f7b3f35,0x3e483f35,0xbe48bf35,0x3f7b3f35,
0x3f0e3f6d,0xbf55bec4,0x3f553ec4,0x3f0e3f6d,0xbf220000,0xbf46bf80,0x3dc93f35,0xbf7fbf35,0xbf62bf7b,0x3ef1be48,0xbf75bf0e,0xbe95bf55,
0x3e95bec4,0x3f753f6d,0xbef1bf6d,0x3f623ec4,0x3f7f3f55,0xbdc93f0e,0x3f463e48,0x3f223f7b,0x3f353f80,0xbf350000,0x3f353f80,0xbf350000,
0xbf350000,0xbf35bf80,0xbf350000,0xbf35bf80,0xbf35bf80,0x3f350000,0xbf35bf80,0x3f350000,0x3f350000,0x3f353f80,0x3f350000,0x3f353f80,
0x3f460000,0x3f223f80,0x3f7f3f35,0xbdc93f35,0x3ef13f7b,0xbf62be48,0xbe953f0e,0xbf75bf55,0xbf75bec4,0xbe95bf6d,0xbf62bf6d,0x3ef1bec4,
0xbdc9bf55,0x3f7f3f0e,0x3f22be48,0x3f463f7b,0xbf0ebf80,0x3f550000,0x3f550000,0x3f0e3f80,0x3f7b3ec4,0x3e483f6d,0x3e483f6d,0xbf7bbec4,
0xbe483f35,0xbf7bbf35,0xbf7bbf35,0x3e48bf35,0xbf55bf6d,0x3f0ebec4,0x3f0ebec4,0x3f553f6d,0xbf620000,0xbef1bf80,0x3e95bf35,0x3f753f35,
0x3dc9bf55,0x3f7f3f0e,0x3f223f7b,0xbf463e48,0x3f463f6d,0xbf223ec4,0xbf7fbec4,0xbdc9bf6d,0xbf75be48,0xbe95bf7b,0x3ef1bf0e,0x3f623f55,
0x3ec43f80,0xbf6d0000,0xbec4bf80,0x3f6d0000,0xbf6dbf35,0x3ec4bf35,0x3f6d3f35,0xbec43f35,0x3f6d0000,0x3ec43f80,0xbf6d0000,0xbec4bf80,
0xbec43f35,0xbf6dbf35,0x3ec4bf35,0x3f6d3f35,0x3f750000,0x3e953f80,0xbf62bf35,0x3ef1bf35,0xbf223f0e,0xbf46bf55,0x3f7f3e48,0x3dc93f7b,
0x3dc9bf6d,0x3f7f3ec4,0xbf463ec4,0xbf22bf6d,0x3ef13f7b,0xbf623e48,0x3e95bf55,0x3f753f0e,0xbe48bf80,0x3f7b0000,0xbf7b0000,0xbe48bf80,
0x3f0e3f6d,0xbf553ec4,0x3f55bec4,0x3f0e3f6d,0xbf55bf35,0x3f0ebf35,0xbf0e3f35,0xbf55bf35,0x3f7b3ec4,0xbe483f6d,0x3e48bf6d,0x3f7b3ec4,
0xbf7f0000,0xbdc9bf80,0xbf223f35,0xbf46bf35,0x3f75be48,0x3e953f7b,0x3ef1bf55,0x3f623f0e,0xbf623ec4,0xbef1bf6d,0xbe953f6d,0xbf75bec4,
0x3f46bf0e,0x3f223f55,0x3dc9bf7b,0x3f7f3e48,0x3f80,0xbf800000,0x3f80,0xbf800000,0xbf80,0x3f800000,0xbf80,0x3f800000,
0x3f80,0xbf800000,0x3f80,0xbf800000,0xbf80,0x3f800000,0xbf80,0x3f800000,0x3f7f0000,0xbdc93f80,0x3f223f35,0xbf463f35,
0xbf75be48,0x3e95bf7b,0xbef1bf55,0x3f62bf0e,0x3f623ec4,0xbef13f6d,0x3e953f6d,0xbf753ec4,0xbf46bf0e,0x3f22bf55,0xbdc9bf7b,0x3f7fbe48,
0x3e48bf80,0x3f7b0000,0x3f7b0000,0xbe483f80,0xbf0e3f6d,0xbf55bec4,0xbf55bec4,0x3f0ebf6d,0x3f55bf35,0x3f0e3f35,0x3f0e3f35,0xbf553f35,
0xbf7b3ec4,0xbe48bf6d,0xbe48bf6d,0x3f7bbec4,0xbf750000,0x3e95bf80,0x3f62bf35,0x3ef13f35,0x3f223f0e,0xbf463f55,0xbf7f3e48,0x3dc9bf7b,
0xbdc9bf6d,0x3f7fbec4,0x3f463ec4,0xbf223f6d,0xbef13f7b,0xbf62be48,0xbe95bf55,0x3f75bf0e,0xbec43f80,0xbf6d0000,0x3ec4bf80,0x3f6d0000,
0x3f6dbf35,0x3ec43f35,0xbf6d3f35,0xbec4bf35,0xbf6d0000,0x3ec4bf80,0x3f6d0000,0xbec43f80,0x3ec43f35,0xbf6d3f35,0xbec4bf35,0x3f6dbf35,
0x3f620000,0xbef13f80,0xbe95bf35,0x3f75bf35,0xbdc9bf55,0x3f7fbf0e,0xbf223f7b,0xbf46be48,0xbf463f6d,0xbf22bec4,0x3f7fbec4,0xbdc93f6d,
0x3f75be48,0xbe953f7b,0xbef1bf0e,0x3f62bf55,0x3f0ebf80,0x3f550000,0xbf550000,0x3f0ebf80,0xbf7b3ec4,0x3e48bf6d,0xbe483f6d,0xbf7b3ec4,
0x3e483f35,0xbf7b3f35,0x3f7bbf35,0x3e483f35,0x3f55bf6d,0x3f0e3ec4,0xbf0ebec4,0x3f55bf6d,0xbf460000,0x3f22bf80,0xbf7f3f35,0xbdc9bf35,
0xbef13f7b,0xbf623e48,0x3e953f0e,0xbf753f55,0x3f75bec4,0xbe953f6d,0x3f62bf6d,0x3ef13ec4,0x3dc9bf55,0x3f7fbf0e,0xbf22be48,0x3f46bf7b,
0xbf353f80,0xbf350000,0xbf353f80,0xbf350000,0x3f350000,0xbf353f80,0x3f350000,0xbf353f80,0x3f35bf80,0x3f350000,0x3f35bf80,0x3f350000,
0xbf350000,0x3f35bf80,0xbf350000,0x3f35bf80,0x3f220000,0xbf463f80,0xbdc93f35,0xbf7f3f35,0x3f62bf7b,0x3ef13e48,0x3f75bf0e,0xbe953f55,
0xbe95bec4,0x3f75bf6d,0x3ef1bf6d,0x3f62bec4,0xbf7f3f55,0xbdc9bf0e,0xbf463e48,0x3f22bf7b,0x3f55bf80,0x3f0e0000,0x3f0e0000,0xbf553f80,
0xbe48bec4,0x3f7bbf6d,0x3f7bbf6d,0x3e483ec4,0xbf7b3f35,0x3e48bf35,0x3e48bf35,0x3f7bbf35,0xbf0e3f6d,0xbf553ec4,0xbf553ec4,0x3f0ebf6d,
0xbef10000,0x3f62bf80,0x3f75bf35,0xbe953f35,0xbf7f3f55,0x3dc9bf0e,0x3f46bf7b,0x3f22be48,0xbf223f6d,0xbf463ec4,0xbdc9bec4,0x3f7fbf6d,
0x3e953e48,0xbf753f7b,0xbf623f0e,0x3ef1bf55,0xbf6d3f80,0xbec40000,0x3f6dbf80,0x3ec40000,0xbec43f35,0xbf6d3f35,0x3ec4bf35,0x3f6dbf35,
0x3ec40000,0xbf6d3f80,0xbec40000,0x3f6dbf80,0x3f6dbf35,0xbec43f35,0xbf6d3f35,0x3ec4bf35,0x3e950000,0xbf753f80,0x3ef1bf35,0x3f62bf35,
0x3f46bf0e,0xbf223f55,0xbdc9be48,0x3f7fbf7b,0x3f7fbf6d,0xbdc93ec4,0xbf223ec4,0x3f46bf6d,0x3f62bf7b,0x3ef1be48,0xbf753f55,0x3e95bf0e,
0x3f7bbf80,0x3e480000,0xbe480000,0x3f7bbf80,0x3f55bf6d,0x3f0ebec4,0xbf0e3ec4,0x3f55bf6d,0x3f0ebf35,0x3f55bf35,0xbf553f35,0x3f0ebf35,
0x3e48bec4,0x3f7bbf6d,0xbf7b3f6d,0x3e48bec4,0xbdc90000,0x3f7fbf80,0xbf463f35,0x3f22bf35,0xbe953e48,0x3f75bf7b,0xbf623f55,0x3ef1bf0e,
0xbef13ec4,0x3f62bf6d,0xbf753f6d,0x3e95bec4,0xbf223f0e,0x3f46bf55,0xbf7f3f7b,0x3dc9be48,0xbf803f80,0x0,0xbf803f80,0x0,
0xbf803f80,0x0,0xbf803f80,0x0,0xbf803f80,0x0,0xbf803f80,0x0,0xbf803f80,0x0,0xbf803f80,0x0,
0xbf7f3f80,0x3dc90000,0xbf223f35,0x3f46bf35,0xbf753f7b,0x3e95be48,0xbef13f0e,0x3f62bf55,0xbf623f6d,0x3ef1bec4,0xbe953ec4,0x3f75bf6d,
0xbf463f55,0x3f22bf0e,0xbdc93e48,0x3f7fbf7b,0xbf7b3f80,0x3e480000,0x3e480000,0x3f7bbf80,0xbf553f6d,0x3f0ebec4,0x3f0ebec4,0x3f55bf6d,
0xbf0e3f35,0x3f55bf35,0x3f55bf35,0x3f0ebf35,0xbe483ec4,0x3f7bbf6d,0x3f7bbf6d,0x3e48bec4,0xbf753f80,0x3e950000,0x3f62bf35,0x3ef1bf35,
0xbf223f55,0x3f46bf0e,0x3f7fbf7b,0xbdc9be48,0xbdc93ec4,0x3f7fbf6d,0x3f46bf6d,0xbf223ec4,0x3ef1be48,0x3f62bf7b,0x3e95bf0e,0xbf753f55,
0xbf6d3f80,0x3ec40000,0x3f6dbf80,0xbec40000,0xbec43f35,0x3f6dbf35,0x3ec4bf35,0xbf6d3f35,0x3ec40000,0x3f6dbf80,0xbec40000,0xbf6d3f80,
0x3f6dbf35,0x3ec4bf35,0xbf6d3f35,0xbec43f35,0xbf623f80,0x3ef10000,0x3e95bf35,0xbf753f35,0xbdc93f0e,0x3f7fbf55,0xbf223e48,0xbf463f7b,
0x3f46bec4,0x3f22bf6d,0xbf7f3f6d,0x3dc93ec4,0x3f75bf7b,0xbe95be48,0xbef13f55,0x3f62bf0e,0xbf553f80,0x3f0e0000,0xbf0e0000,0xbf553f80,
0x3e483ec4,0x3f7bbf6d,0xbf7b3f6d,0x3e483ec4,0x3f7bbf35,0x3e48bf35,0xbe483f35,0x3f7bbf35,0x3f0ebf6d,0xbf553ec4,0x3f55bec4,0x3f0ebf6d,
0xbf463f80,0x3f220000,0xbf7f3f35,0xbdc93f35,0x3ef13e48,0x3f62bf7b,0xbe953f55,0x3f75bf0e,0x3f75bf6d,0xbe95bec4,0x3f62bec4,0x3ef1bf6d,
0xbdc9bf0e,0xbf7f3f55,0x3f22bf7b,0xbf463e48,0xbf353f80,0x3f350000,0xbf353f80,0x3f350000,0x3f350000,0x3f35bf80,0x3f350000,0x3f35bf80,
0x3f35bf80,0xbf350000,0x3f35bf80,0xbf350000,0xbf350000,0xbf353f80,0xbf350000,0xbf353f80,0xbf223f80,0x3f460000,0x3dc93f35,0x3f7fbf35,
0x3f62be48,0x3ef1bf7b,0x3f75bf55,0xbe95bf0e,0x3e95bf6d,0xbf753ec4,0xbef1bec4,0xbf623f6d,0xbf7f3f0e,0xbdc93f55,0xbf463f7b,0x3f223e48,
0xbf0e3f80,0x3f550000,0x3f550000,0x3f0ebf80,0x3f7bbec4,0x3e48bf6d,0x3e48bf6d,0xbf7b3ec4,0xbe48bf35,0xbf7b3f35,0xbf7b3f35,0x3e483f35,
0xbf553f6d,0x3f0e3ec4,0x3f0e3ec4,0x3f55bf6d,0xbef13f80,0x3f620000,0x3f75bf35,0xbe95bf35,0x3f7fbf0e,0xbdc9bf55,0xbf46be48,0xbf223f7b,
0xbf22bec4,0xbf463f6d,0xbdc93f6d,0x3f7fbec4,0xbe953f7b,0x3f75be48,0x3f62bf55,0xbef1bf0e,0xbec43f80,0x3f6d0000,0x3ec4bf80,0xbf6d0000,
0x3f6dbf35,0xbec4bf35,0xbf6d3f35,0x3ec43f35,0xbf6d0000,0xbec43f80,0x3f6d0000,0x3ec4bf80,0x3ec43f35,0x3f6dbf35,0xbec4bf35,0xbf6d3f35,
0xbe953f80,0x3f750000,0xbef1bf35,0xbf623f35,0x3f46bf55,0xbf22bf0e,0xbdc93f7b,0x3f7fbe48,0xbf7f3ec4,0x3dc93f6d,0x3f22bf6d,0xbf46bec4,
0x3f623e48,0x3ef1bf7b,0xbf753f0e,0x3e953f55,0xbe483f80,0x3f7b0000,0xbf7b0000,0xbe483f80,0x3f0ebf6d,0xbf55bec4,0x3f553ec4,0x3f0ebf6d,
0xbf553f35,0x3f0e3f35,0xbf0ebf35,0xbf553f35,0x3f7bbec4,0xbe48bf6d,0x3e483f6d,0x3f7bbec4,0xbdc93f80,0x3f7f0000,0xbf463f35,0x3f223f35,
0x3e95bf7b,0xbf75be48,0x3f62bf0e,0xbef1bf55,0xbef13f6d,0x3f623ec4,0xbf753ec4,0x3e953f6d,0x3f22bf55,0xbf46bf0e,0x3f7fbe48,0xbdc9bf7b,
0x3f80,0x3f800000,0x3f80,0x3f800000,0xbf80,0xbf800000,0xbf80,0xbf800000,0x3f80,0x3f800000,0x3f80,0x3f800000,
0xbf80,0xbf800000,0xbf80,0xbf800000,0x3dc93f80,0x3f7f0000,0x3f463f35,0x3f22bf35,0xbe95bf7b,0xbf753e48,0xbf62bf0e,0xbef13f55,
0x3ef13f6d,0x3f62bec4,0x3f753ec4,0x3e95bf6d,0xbf22bf55,0xbf463f0e,0xbf7fbe48,0xbdc93f7b,0x3e483f80,0x3f7b0000,0x3f7b0000,0xbe48bf80,
0xbf0ebf6d,0xbf553ec4,0xbf553ec4,0x3f0e3f6d,0x3f553f35,0x3f0ebf35,0x3f0ebf35,0xbf55bf35,0xbf7bbec4,0xbe483f6d,0xbe483f6d,0x3f7b3ec4,
0x3e953f80,0x3f750000,0x3ef1bf35,0xbf62bf35,0xbf46bf55,0xbf223f0e,0x3dc93f7b,0x3f7f3e48,0x3f7f3ec4,0x3dc9bf6d,0xbf22bf6d,0xbf463ec4,
0xbf623e48,0x3ef13f7b,0x3f753f0e,0x3e95bf55,0x3ec43f80,0x3f6d0000,0xbec4bf80,0xbf6d0000,0xbf6dbf35,0xbec43f35,0x3f6d3f35,0x3ec4bf35,
0x3f6d0000,0xbec4bf80,0xbf6d0000,0x3ec43f80,0xbec43f35,0x3f6d3f35,0x3ec4bf35,0xbf6dbf35,0x3ef13f80,0x3f620000,0xbf75bf35,0xbe953f35,
0xbf7fbf0e,0xbdc93f55,0x3f46be48,0xbf22bf7b,0x3f22bec4,0xbf46bf6d,0x3dc93f6d,0x3f7f3ec4,0x3e953f7b,0x3f753e48,0xbf62bf55,0xbef13f0e,
0x3f0e3f80,0x3f550000,0xbf550000,0x3f0e3f80,0xbf7bbec4,0x3e483f6d,0xbe48bf6d,0xbf7bbec4,0x3e48bf35,0xbf7bbf35,0x3f7b3f35,0x3e48bf35,
0x3f553f6d,0x3f0ebec4,0xbf0e3ec4,0x3f553f6d,0x3f223f80,0x3f460000,0xbdc93f35,0x3f7f3f35,0xbf62be48,0x3ef13f7b,0xbf75bf55,0xbe953f0e,
0xbe95bf6d,0xbf75bec4,0x3ef1bec4,0xbf62bf6d,0x3f7f3f0e,0xbdc9bf55,0x3f463f7b,0x3f22be48,0x3f353f80,0x3f350000,0x3f353f80,0x3f350000,
0xbf350000,0x3f353f80,0xbf350000,0x3f353f80,0xbf35bf80,0xbf350000,0xbf35bf80,0xbf350000,0x3f350000,0xbf35bf80,0x3f350000,0xbf35bf80,
0x3f463f80,0x3f220000,0x3f7f3f35,0xbdc9bf35,0xbef13e48,0x3f623f7b,0x3e953f55,0x3f753f0e,0xbf75bf6d,0xbe953ec4,0xbf62bec4,0x3ef13f6d,
0x3dc9bf0e,0xbf7fbf55,0xbf22bf7b,0xbf46be48,0x3f553f80,0x3f0e0000,0x3f0e0000,0xbf55bf80,0xbe483ec4,0x3f7b3f6d,0x3f7b3f6d,0x3e48bec4,
0xbf7bbf35,0x3e483f35,0x3e483f35,0x3f7b3f35,0xbf0ebf6d,0xbf55bec4,0xbf55bec4,0x3f0e3f6d,0x3f623f80,0x3ef10000,0xbe95bf35,0xbf75bf35,
0x3dc93f0e,0x3f7f3f55,0x3f223e48,0xbf46bf7b,0xbf46bec4,0x3f223f6d,0x3f7f3f6d,0x3dc9bec4,0xbf75bf7b,0xbe953e48,0x3ef13f55,0x3f623f0e,
0x3f6d3f80,0x3ec40000,0xbf6dbf80,0xbec40000,0x3ec43f35,0x3f6d3f35,0xbec4bf35,0xbf6dbf35,0xbec40000,0x3f6d3f80,0x3ec40000,0xbf6dbf80,
0xbf6dbf35,0x3ec43f35,0x3f6d3f35,0xbec4bf35,0x3f753f80,0x3e950000,0xbf62bf35,0x3ef13f35,0x3f223f55,0x3f463f0e,0xbf7fbf7b,0xbdc93e48,
0x3dc93ec4,0x3f7f3f6d,0xbf46bf6d,0xbf22bec4,0xbef1be48,0x3f623f7b,0xbe95bf0e,0xbf75bf55,0x3f7b3f80,0x3e480000,0xbe480000,0x3f7b3f80,
0x3f553f6d,0x3f0e3ec4,0xbf0ebec4,0x3f553f6d,0x3f0e3f35,0x3f553f35,0xbf55bf35,0x3f0e3f35,0x3e483ec4,0x3f7b3f6d,0xbf7bbf6d,0x3e483ec4,
0x3f7f3f80,0x3dc90000,0x3f223f35,0x3f463f35,0x3f753f7b,0x3e953e48,0x3ef13f0e,0x3f623f55,0x3f623f6d,0x3ef13ec4,0x3e953ec4,0x3f753f6d,
0x3f463f55,0x3f223f0e,0x3dc93e48,0x3f7f3f7b,0xbf803f80,0x0,0xbf803f80,0x0,0xbf803f80,0x0,0xbf803f80,0x0,
0xbf803f80,0x0,0xbf803f80,0x0,0xbf803f80,0x0,0xbf803f80,0x0,0x3dc90000,0x3f7fbf80,0x3f46bf35,0x3f22bf35,
0x3e95be48,0x3f75bf7b,0x3f62bf55,0x3ef1bf0e,0x3ef1bec4,0x3f62bf6d,0x3f75bf6d,0x3e95bec4,0x3f22bf0e,0x3f46bf55,0x3f7fbf7b,0x3dc9be48,
0x3f7bbf80,0xbe480000,0xbe480000,0xbf7b3f80,0x3f55bf6d,0xbf0e3ec4,0xbf0e3ec4,0xbf553f6d,0x3f0ebf35,0xbf553f35,0xbf553f35,0xbf0e3f35,
0x3e48bec4,0xbf7b3f6d,0xbf7b3f6d,0xbe483ec4,0xbe950000,0xbf753f80,0xbef13f35,0x3f62bf35,0xbf463f0e,0xbf223f55,0x3dc93e48,0x3f7fbf7b,
0xbf7f3f6d,0xbdc93ec4,0x3f22bec4,0x3f46bf6d,0xbf623f7b,0x3ef1be48,0x3f75bf55,0x3e95bf0e,0xbf6d3f80,0x3ec40000,0x3f6dbf80,0xbec40000,
0xbec43f35,0x3f6dbf35,0x3ec4bf35,0xbf6d3f35,0x3ec40000,0x3f6dbf80,0xbec40000,0xbf6d3f80,0x3f6dbf35,0x3ec4bf35,0xbf6d3f35,0xbec43f35,
0x3ef10000,0x3f62bf80,0xbf753f35,0xbe953f35,0x3f7fbf55,0x3dc9bf0e,0xbf463f7b,0x3f22be48,0x3f22bf6d,0xbf463ec4,0x3dc93ec4,0x3f7fbf6d,
0xbe95be48,0xbf753f7b,0x3f62bf0e,0x3ef1bf55,0x3f55bf80,0xbf0e0000,0x3f0e0000,0x3f55bf80,0xbe48bec4,0xbf7b3f6d,0x3f7bbf6d,0xbe48bec4,
0xbf7b3f35,0xbe483f35,0x3e48bf35,0xbf7b3f35,0xbf0e3f6d,0x3f55bec4,0xbf553ec4,0xbf0e3f6d,0xbf220000,0xbf463f80,0x3dc9bf35,0xbf7f3f35,
0xbf623f7b,0x3ef13e48,0xbf753f0e,0xbe953f55,0x3e953ec4,0x3f75bf6d,0xbef13f6d,0x3f62bec4,0x3f7fbf55,0xbdc9bf0e,0x3f46be48,0x3f22bf7b,
0xbf353f80,0x3f350000,0xbf353f80,0x3f350000,0x3f350000,0x3f35bf80,0x3f350000,0x3f35bf80,0x3f35bf80,0xbf350000,0x3f35bf80,0xbf350000,
0xbf350000,0xbf353f80,0xbf350000,0xbf353f80,0x3f460000,0x3f22bf80,0x3f7fbf35,0xbdc9bf35,0x3ef1bf7b,0xbf623e48,0xbe95bf0e,0xbf753f55,
0xbf753ec4,0xbe953f6d,0xbf623f6d,0x3ef13ec4,0xbdc93f55,0x3f7fbf0e,0x3f223e48,0x3f46bf7b,0x3f0ebf80,0xbf550000,0xbf550000,0xbf0e3f80,
0xbf7b3ec4,0xbe483f6d,0xbe483f6d,0x3f7bbec4,0x3e483f35,0x3f7bbf35,0x3f7bbf35,0xbe48bf35,0x3f55bf6d,0xbf0ebec4,0xbf0ebec4,0xbf553f6d,
0xbf620000,0xbef13f80,0x3e953f35,0x3f75bf35,0x3dc93f55,0x3f7fbf0e,0x3f22bf7b,0xbf46be48,0x3f46bf6d,0xbf22bec4,0xbf7f3ec4,0xbdc93f6d,
0xbf753e48,0xbe953f7b,0x3ef13f0e,0x3f62bf55,0xbec43f80,0x3f6d0000,0x3ec4bf80,0xbf6d0000,0x3f6dbf35,0xbec4bf35,0xbf6d3f35,0x3ec43f35,
0xbf6d0000,0xbec43f80,0x3f6d0000,0x3ec4bf80,0x3ec43f35,0x3f6dbf35,0xbec4bf35,0xbf6d3f35,0x3f750000,0x3e95bf80,0xbf623f35,0x3ef13f35,
0xbf22bf0e,0xbf463f55,0x3f7fbe48,0x3dc9bf7b,0x3dc93f6d,0x3f7fbec4,0xbf46bec4,0xbf223f6d,0x3ef1bf7b,0xbf62be48,0x3e953f55,0x3f75bf0e,
0x3e48bf80,0xbf7b0000,0x3f7b0000,0x3e48bf80,0xbf0e3f6d,0x3f553ec4,0xbf55bec4,0xbf0e3f6d,0x3f55bf35,0xbf0ebf35,0x3f0e3f35,0x3f55bf35,
0xbf7b3ec4,0x3e483f6d,0xbe48bf6d,0xbf7b3ec4,0xbf7f0000,0xbdc93f80,0xbf22bf35,0xbf463f35,0x3f753e48,0x3e95bf7b,0x3ef13f55,0x3f62bf0e,
0xbf62bec4,0xbef13f6d,0xbe95bf6d,0xbf753ec4,0x3f463f0e,0x3f22bf55,0x3dc93f7b,0x3f7fbe48,0x3f80,0x3f800000,0x3f80,0x3f800000,
0xbf80,0xbf800000,0xbf80,0xbf800000,0x3f80,0x3f800000,0x3f80,0x3f800000,0xbf80,0xbf800000,0xbf80,0xbf800000,
0x3f7f0000,0xbdc9bf80,0x3f22bf35,0xbf46bf35,0xbf753e48,0x3e953f7b,0xbef13f55,0x3f623f0e,0x3f62bec4,0xbef1bf6d,0x3e95bf6d,0xbf75bec4,
0xbf463f0e,0x3f223f55,0xbdc93f7b,0x3f7f3e48,0xbe48bf80,0xbf7b0000,0xbf7b0000,0x3e483f80,0x3f0e3f6d,0x3f55bec4,0x3f55bec4,0xbf0ebf6d,
0xbf55bf35,0xbf0e3f35,0xbf0e3f35,0x3f553f35,0x3f7b3ec4,0x3e48bf6d,0x3e48bf6d,0xbf7bbec4,0xbf750000,0x3e953f80,0x3f623f35,0x3ef1bf35,
0x3f22bf0e,0xbf46bf55,0xbf7fbe48,0x3dc93f7b,0xbdc93f6d,0x3f7f3ec4,0x3f46bec4,0xbf22bf6d,0xbef1bf7b,0xbf623e48,0xbe953f55,0x3f753f0e,
0x3ec43f80,0x3f6d0000,0xbec4bf80,0xbf6d0000,0xbf6dbf35,0xbec43f35,0x3f6d3f35,0x3ec4bf35,0x3f6d0000,0xbec4bf80,0xbf6d0000,0x3ec43f80,
0xbec43f35,0x3f6d3f35,0x3ec4bf35,0xbf6dbf35,0x3f620000,0xbef1bf80,0xbe953f35,0x3f753f35,0xbdc93f55,0x3f7f3f0e,0xbf22bf7b,0xbf463e48,
0xbf46bf6d,0xbf223ec4,0x3f7f3ec4,0xbdc9bf6d,0x3f753e48,0xbe95bf7b,0xbef13f0e,0x3f623f55,0xbf0ebf80,0xbf550000,0x3f550000,0xbf0ebf80,
0x3f7b3ec4,0xbe48bf6d,0x3e483f6d,0x3f7b3ec4,0xbe483f35,0x3f7b3f35,0xbf7bbf35,0xbe483f35,0xbf55bf6d,0xbf0e3ec4,0x3f0ebec4,0xbf55bf6d,
0xbf460000,0x3f223f80,0xbf7fbf35,0xbdc93f35,0xbef1bf7b,0xbf62be48,0x3e95bf0e,0xbf75bf55,0x3f753ec4,0xbe95bf6d,0x3f623f6d,0x3ef1bec4,
0x3dc93f55,0x3f7f3f0e,0xbf223e48,0x3f463f7b,0x3f353f80,0x3f350000,0x3f353f80,0x3f350000,0xbf350000,0x3f353f80,0xbf350000,0x3f353f80,
0xbf35bf80,0xbf350000,0xbf35bf80,0xbf350000,0x3f350000,0xbf35bf80,0x3f350000,0xbf35bf80,0x3f220000,0xbf46bf80,0xbdc9bf35,0xbf7fbf35,
0x3f623f7b,0x3ef1be48,0x3f753f0e,0xbe95bf55,0xbe953ec4,0x3f753f6d,0x3ef13f6d,0x3f623ec4,0xbf7fbf55,0xbdc93f0e,0xbf46be48,0x3f223f7b,
0xbf55bf80,0xbf0e0000,0xbf0e0000,0x3f553f80,0x3e48bec4,0xbf7bbf6d,0xbf7bbf6d,0xbe483ec4,0x3f7b3f35,0xbe48bf35,0xbe48bf35,0xbf7bbf35,
0x3f0e3f6d,0x3f553ec4,0x3f553ec4,0xbf0ebf6d,0xbef10000,0x3f623f80,0x3f753f35,0xbe95bf35,0xbf7fbf55,0x3dc93f0e,0x3f463f7b,0x3f223e48,
0xbf22bf6d,0xbf46bec4,0xbdc93ec4,0x3f7f3f6d,0x3e95be48,0xbf75bf7b,0xbf62bf0e,0x3ef13f55,0x3f6d3f80,0x3ec40000,0xbf6dbf80,0xbec40000,
0x3ec43f35,0x3f6d3f35,0xbec4bf35,0xbf6dbf35,0xbec40000,0x3f6d3f80,0x3ec40000,0xbf6dbf80,0xbf6dbf35,0x3ec43f35,0x3f6d3f35,0xbec4bf35,
0x3e950000,0xbf75bf80,0x3ef13f35,0x3f623f35,0x3f463f0e,0xbf22bf55,0xbdc93e48,0x3f7f3f7b,0x3f7f3f6d,0xbdc9bec4,0xbf22bec4,0x3f463f6d,
0x3f623f7b,0x3ef13e48,0xbf75bf55,0x3e953f0e,0xbf7bbf80,0xbe480000,0x3e480000,0xbf7bbf80,0xbf55bf6d,0xbf0ebec4,0x3f0e3ec4,0xbf55bf6d,
0xbf0ebf35,0xbf55bf35,0x3f553f35,0xbf0ebf35,0xbe48bec4,0xbf7bbf6d,0x3f7b3f6d,0xbe48bec4,0xbdc90000,0x3f7f3f80,0xbf46bf35,0x3f223f35,
0xbe95be48,0x3f753f7b,0xbf62bf55,0x3ef13f0e,0xbef1bec4,0x3f623f6d,0xbf75bf6d,0x3e953ec4,0xbf22bf0e,0x3f463f55,0xbf7fbf7b,0x3dc93e48,
0xbf803f80,0x0,0xbf803f80,0x0,0xbf803f80,0x0,0xbf803f80,0x0,0xbf803f80,0x0,0xbf803f80,0x0,
0xbf803f80,0x0,0xbf803f80,0x0,0x3f7fbf80,0xbdc90000,0x3f22bf35,0xbf463f35,0x3f75bf7b,0xbe953e48,0x3ef1bf0e,0xbf623f55,
0x3f62bf6d,0xbef13ec4,0x3e95bec4,0xbf753f6d,0x3f46bf55,0xbf223f0e,0x3dc9be48,0xbf7f3f7b,0xbf7b3f80,0x3e480000,0x3e480000,0x3f7bbf80,
0xbf553f6d,0x3f0ebec4,0x3f0ebec4,0x3f55bf6d,0xbf0e3f35,0x3f55bf35,0x3f55bf35,0x3f0ebf35,0xbe483ec4,0x3f7bbf6d,0x3f7bbf6d,0x3e48bec4,
0x3f75bf80,0xbe950000,0xbf623f35,0xbef13f35,0x3f22bf55,0xbf463f0e,0xbf7f3f7b,0x3dc93e48,0x3dc9bec4,0xbf7f3f6d,0xbf463f6d,0x3f22bec4,
0xbef13e48,0xbf623f7b,0xbe953f0e,0x3f75bf55,0xbf6d3f80,0x3ec40000,0x3f6dbf80,0xbec40000,0xbec43f35,0x3f6dbf35,0x3ec4bf35,0xbf6d3f35,
0x3ec40000,0x3f6dbf80,0xbec40000,0xbf6d3f80,0x3f6dbf35,0x3ec4bf35,0xbf6d3f35,0xbec43f35,0x3f62bf80,0xbef10000,0xbe953f35,0x3f75bf35,
0x3dc9bf0e,0xbf7f3f55,0x3f22be48,0x3f46bf7b,0xbf463ec4,0xbf223f6d,0x3f7fbf6d,0xbdc9bec4,0xbf753f7b,0x3e953e48,0x3ef1bf55,0xbf623f0e,
0xbf553f80,0x3f0e0000,0xbf0e0000,0xbf553f80,0x3e483ec4,0x3f7bbf6d,0xbf7b3f6d,0x3e483ec4,0x3f7bbf35,0x3e48bf35,0xbe483f35,0x3f7bbf35,
0x3f0ebf6d,0xbf553ec4,0x3f55bec4,0x3f0ebf6d,0x3f46bf80,0xbf220000,0x3f7fbf35,0x3dc9bf35,0xbef1be48,0xbf623f7b,0x3e95bf55,0xbf753f0e,
0xbf753f6d,0x3e953ec4,0xbf623ec4,0xbef13f6d,0x3dc93f0e,0x3f7fbf55,0xbf223f7b,0x3f46be48,0xbf353f80,0x3f350000,0xbf353f80,0x3f350000,
0x3f350000,0x3f35bf80,0x3f350000,0x3f35bf80,0x3f35bf80,0xbf350000,0x3f35bf80,0xbf350000,0xbf350000,0xbf353f80,0xbf350000,0xbf353f80,
0x3f22bf80,0xbf460000,0xbdc9bf35,0xbf7f3f35,0xbf623e48,0xbef13f7b,0xbf753f55,0x3e953f0e,0xbe953f6d,0x3f75bec4,0x3ef13ec4,0x3f62bf6d,
0x3f7fbf0e,0x3dc9bf55,0x3f46bf7b,0xbf22be48,0xbf0e3f80,0x3f550000,0x3f550000,0x3f0ebf80,0x3f7bbec4,0x3e48bf6d,0x3e48bf6d,0xbf7b3ec4,
0xbe48bf35,0xbf7b3f35,0xbf7b3f35,0x3e483f35,0xbf553f6d,0x3f0e3ec4,0x3f0e3ec4,0x3f55bf6d,0x3ef1bf80,0xbf620000,0xbf753f35,0x3e953f35,
0xbf7f3f0e,0x3dc93f55,0x3f463e48,0x3f22bf7b,0x3f223ec4,0x3f46bf6d,0x3dc9bf6d,0xbf7f3ec4,0x3e95bf7b,0xbf753e48,0xbf623f55,0x3ef13f0e,
0xbec43f80,0x3f6d0000,0x3ec4bf80,0xbf6d0000,0x3f6dbf35,0xbec4bf35,0xbf6d3f35,0x3ec43f35,0xbf6d0000,0xbec43f80,0x3f6d0000,0x3ec4bf80,
0x3ec43f35,0x3f6dbf35,0xbec4bf35,0xbf6d3f35,0x3e95bf80,0xbf750000,0x3ef13f35,0x3f62bf35,0xbf463f55,0x3f223f0e,0x3dc9bf7b,0xbf7f3e48,
0x3f7fbec4,0xbdc9bf6d,0xbf223f6d,0x3f463ec4,0xbf62be48,0xbef13f7b,0x3f75bf0e,0xbe95bf55,0xbe483f80,0x3f7b0000,0xbf7b0000,0xbe483f80,
0x3f0ebf6d,0xbf55bec4,0x3f553ec4,0x3f0ebf6d,0xbf553f35,0x3f0e3f35,0xbf0ebf35,0xbf553f35,0x3f7bbec4,0xbe48bf6d,0x3e483f6d,0x3f7bbec4,
0x3dc9bf80,0xbf7f0000,0x3f46bf35,0xbf22bf35,0xbe953f7b,0x3f753e48,0xbf623f0e,0x3ef13f55,0x3ef1bf6d,0xbf62bec4,0x3f75bec4,0xbe95bf6d,
0xbf223f55,0x3f463f0e,0xbf7f3e48,0x3dc93f7b,0x3f80,0x3f800000,0x3f80,0x3f800000,0xbf80,0xbf800000,0xbf80,0xbf800000,
0x3f80,0x3f800000,0x3f80,0x3f800000,0xbf80,0xbf800000,0xbf80,0xbf800000,0xbdc9bf80,0xbf7f0000,0xbf46bf35,0xbf223f35,
0x3e953f7b,0x3f75be48,0x3f623f0e,0x3ef1bf55,0xbef1bf6d,0xbf623ec4,0xbf75bec4,0xbe953f6d,0x3f223f55,0x3f46bf0e,0x3f7f3e48,0x3dc9bf7b,
0x3e483f80,0x3f7b0000,0x3f7b0000,0xbe48bf80,0xbf0ebf6d,0xbf553ec4,0xbf553ec4,0x3f0e3f6d,0x3f553f35,0x3f0ebf35,0x3f0ebf35,0xbf55bf35,
0xbf7bbec4,0xbe483f6d,0xbe483f6d,0x3f7b3ec4,0xbe95bf80,0xbf750000,0xbef13f35,0x3f623f35,0x3f463f55,0x3f22bf0e,0xbdc9bf7b,0xbf7fbe48,
0xbf7fbec4,0xbdc93f6d,0x3f223f6d,0x3f46bec4,0x3f62be48,0xbef1bf7b,0xbf75bf0e,0xbe953f55,0x3ec43f80,0x3f6d0000,0xbec4bf80,0xbf6d0000,
0xbf6dbf35,0xbec43f35,0x3f6d3f35,0x3ec4bf35,0x3f6d0000,0xbec4bf80,0xbf6d0000,0x3ec43f80,0xbec43f35,0x3f6d3f35,0x3ec4bf35,0xbf6dbf35,
0xbef1bf80,0xbf620000,0x3f753f35,0x3e95bf35,0x3f7f3f0e,0x3dc9bf55,0xbf463e48,0x3f223f7b,0xbf223ec4,0x3f463f6d,0xbdc9bf6d,0xbf7fbec4,
0xbe95bf7b,0xbf75be48,0x3f623f55,0x3ef1bf0e,0x3f0e3f80,0x3f550000,0xbf550000,0x3f0e3f80,0xbf7bbec4,0x3e483f6d,0xbe48bf6d,0xbf7bbec4,
0x3e48bf35,0xbf7bbf35,0x3f7b3f35,0x3e48bf35,0x3f553f6d,0x3f0ebec4,0xbf0e3ec4,0x3f553f6d,0xbf22bf80,0xbf460000,0x3dc9bf35,0xbf7fbf35,
0x3f623e48,0xbef1bf7b,0x3f753f55,0x3e95bf0e,0x3e953f6d,0x3f753ec4,0xbef13ec4,0x3f623f6d,0xbf7fbf0e,0x3dc93f55,0xbf46bf7b,0xbf223e48,
0x3f353f80,0x3f350000,0x3f353f80,0x3f350000,0xbf350000,0x3f353f80,0xbf350000,0x3f353f80,0xbf35bf80,0xbf350000,0xbf35bf80,0xbf350000,
0x3f350000,0xbf35bf80,0x3f350000,0xbf35bf80,0xbf46bf80,0xbf220000,0xbf7fbf35,0x3dc93f35,0x3ef1be48,0xbf62bf7b,0xbe95bf55,0xbf75bf0e,
0x3f753f6d,0x3e95bec4,0x3f623ec4,0xbef1bf6d,0xbdc93f0e,0x3f7f3f55,0x3f223f7b,0x3f463e48,0x3f553f80,0x3f0e0000,0x3f0e0000,0xbf55bf80,
0xbe483ec4,0x3f7b3f6d,0x3f7b3f6d,0x3e48bec4,0xbf7bbf35,0x3e483f35,0x3e483f35,0x3f7b3f35,0xbf0ebf6d,0xbf55bec4,0xbf55bec4,0x3f0e3f6d,
0xbf62bf80,0xbef10000,0x3e953f35,0x3f753f35,0xbdc9bf0e,0xbf7fbf55,0xbf22be48,0x3f463f7b,0x3f463ec4,0xbf22bf6d,0xbf7fbf6d,0xbdc93ec4,
0x3f753f7b,0x3e95be48,0xbef1bf55,0xbf62bf0e,0x3f6d3f80,0x3ec40000,0xbf6dbf80,0xbec40000,0x3ec43f35,0x3f6d3f35,0xbec4bf35,0xbf6dbf35,
0xbec40000,0x3f6d3f80,0x3ec40000,0xbf6dbf80,0xbf6dbf35,0x3ec43f35,0x3f6d3f35,0xbec4bf35,0xbf75bf80,0xbe950000,0x3f623f35,0xbef1bf35,
0xbf22bf55,0xbf46bf0e,0x3f7f3f7b,0x3dc9be48,0xbdc9bec4,0xbf7fbf6d,0x3f463f6d,0x3f223ec4,0x3ef13e48,0xbf62bf7b,0x3e953f0e,0x3f753f55,
0x3f7b3f80,0x3e480000,0xbe480000,0x3f7b3f80,0x3f553f6d,0x3f0e3ec4,0xbf0ebec4,0x3f553f6d,0x3f0e3f35,0x3f553f35,0xbf55bf35,0x3f0e3f35,
0x3e483ec4,0x3f7b3f6d,0xbf7bbf6d,0x3e483ec4,0xbf7fbf80,0xbdc90000,0xbf22bf35,0xbf46bf35,0xbf75bf7b,0xbe95be48,0xbef1bf0e,0xbf62bf55,
0xbf62bf6d,0xbef1bec4,0xbe95bec4,0xbf75bf6d,0xbf46bf55,0xbf22bf0e,0xbdc9be48,0xbf7fbf7b,0xbf803f80,0x0,0xbf803f80,0x0,
0xbf803f80,0x0,0xbf803f80,0x0,0xbf803f80,0x0,0xbf803f80,0x0,0xbf803f80,0x0,0xbf803f80,0x0,
0xbdc90000,0xbf7f3f80,0xbf463f35,0xbf223f35,0xbe953e48,0xbf753f7b,0xbf623f55,0xbef13f0e,0xbef13ec4,0xbf623f6d,0xbf753f6d,0xbe953ec4,
0xbf223f0e,0xbf463f55,0xbf7f3f7b,0xbdc93e48,0x3f7bbf80,0xbe480000,0xbe480000,0xbf7b3f80,0x3f55bf6d,0xbf0e3ec4,0xbf0e3ec4,0xbf553f6d,
0x3f0ebf35,0xbf553f35,0xbf553f35,0xbf0e3f35,0x3e48bec4,0xbf7b3f6d,0xbf7b3f6d,0xbe483ec4,0x3e950000,0x3f75bf80,0x3ef1bf35,0xbf623f35,
0x3f46bf0e,0x3f22bf55,0xbdc9be48,0xbf7f3f7b,0x3f7fbf6d,0x3dc9bec4,0xbf223ec4,0xbf463f6d,0x3f62bf7b,0xbef13e48,0xbf753f55,0xbe953f0e,
0xbf6d3f80,0x3ec40000,0x3f6dbf80,0xbec40000,0xbec43f35,0x3f6dbf35,0x3ec4bf35,0xbf6d3f35,0x3ec40000,0x3f6dbf80,0xbec40000,0xbf6d3f80,
0x3f6dbf35,0x3ec4bf35,0xbf6d3f35,0xbec43f35,0xbef10000,0xbf623f80,0x3f75bf35,0x3e95bf35,0xbf7f3f55,0xbdc93f0e,0x3f46bf7b,0xbf223e48,
0xbf223f6d,0x3f46bec4,0xbdc9bec4,0xbf7f3f6d,0x3e953e48,0x3f75bf7b,0xbf623f0e,0xbef13f55,0x3f55bf80,0xbf0e0000,0x3f0e0000,0x3f55bf80,
0xbe48bec4,0xbf7b3f6d,0x3f7bbf6d,0xbe48bec4,0xbf7b3f35,0xbe483f35,0x3e48bf35,0xbf7b3f35,0xbf0e3f6d,0x3f55bec4,0xbf553ec4,0xbf0e3f6d,
0x3f220000,0x3f46bf80,0xbdc93f35,0x3f7fbf35,0x3f62bf7b,0xbef1be48,0x3f75bf0e,0x3e95bf55,0xbe95bec4,0xbf753f6d,0x3ef1bf6d,0xbf623ec4,
0xbf7f3f55,0x3dc93f0e,0xbf463e48,0xbf223f7b,0xbf353f80,0x3f350000,0xbf353f80,0x3f350000,0x3f350000,0x3f35bf80,0x3f350000,0x3f35bf80,
0x3f35bf80,0xbf350000,0x3f35bf80,0xbf350000,0xbf350000,0xbf353f80,0xbf350000,0xbf353f80,0xbf460000,0xbf223f80,0xbf7f3f35,0x3dc93f35,
0xbef13f7b,0x3f62be48,0x3e953f0e,0x3f75bf55,0x3f75bec4,0x3e95bf6d,0x3f62bf6d,0xbef1bec4,0x3dc9bf55,0xbf7f3f0e,0xbf22be48,0xbf463f7b,
0x3f0ebf80,0xbf550000,0xbf550000,0xbf0e3f80,0xbf7b3ec4,0xbe483f6d,0xbe483f6d,0x3f7bbec4,0x3e483f35,0x3f7bbf35,0x3f7bbf35,0xbe48bf35,
0x3f55bf6d,0xbf0ebec4,0xbf0ebec4,0xbf553f6d,0x3f620000,0x3ef1bf80,0xbe95bf35,0xbf753f35,0xbdc9bf55,0xbf7f3f0e,0xbf223f7b,0x3f463e48,
0xbf463f6d,0x3f223ec4,0x3f7fbec4,0x3dc9bf6d,0x3f75be48,0x3e95bf7b,0xbef1bf0e,0xbf623f55,0xbec43f80,0x3f6d0000,0x3ec4bf80,0xbf6d0000,
0x3f6dbf35,0xbec4bf35,0xbf6d3f35,0x3ec43f35,0xbf6d0000,0xbec43f80,0x3f6d0000,0x3ec4bf80,0x3ec43f35,0x3f6dbf35,0xbec4bf35,0xbf6d3f35,
0xbf750000,0xbe953f80,0x3f62bf35,0xbef1bf35,0x3f223f0e,0x3f46bf55,0xbf7f3e48,0xbdc93f7b,0xbdc9bf6d,0xbf7f3ec4,0x3f463ec4,0x3f22bf6d,
0xbef13f7b,0x3f623e48,0xbe95bf55,0xbf753f0e,0x3e48bf80,0xbf7b0000,0x3f7b0000,0x3e48bf80,0xbf0e3f6d,0x3f553ec4,0xbf55bec4,0xbf0e3f6d,
0x3f55bf35,0xbf0ebf35,0x3f0e3f35,0x3f55bf35,0xbf7b3ec4,0x3e483f6d,0xbe48bf6d,0xbf7b3ec4,0x3f7f0000,0x3dc9bf80,0x3f223f35,0x3f46bf35,
0xbf75be48,0xbe953f7b,0xbef1bf55,0xbf623f0e,0x3f623ec4,0x3ef1bf6d,0x3e953f6d,0x3f75bec4,0xbf46bf0e,0xbf223f55,0xbdc9bf7b,0xbf7f3e48,
0x3f80,0x3f800000,0x3f80,0x3f800000,0xbf80,0xbf800000,0xbf80,0xbf800000,0x3f80,0x3f800000,0x3f80,0x3f800000,
0xbf80,0xbf800000,0xbf80,0xbf800000,0xbf7f0000,0x3dc93f80,0xbf223f35,0x3f463f35,0x3f75be48,0xbe95bf7b,0x3ef1bf55,0xbf62bf0e,
0xbf623ec4,0x3ef13f6d,0xbe953f6d,0x3f753ec4,0x3f46bf0e,0xbf22bf55,0x3dc9bf7b,0xbf7fbe48,0xbe48bf80,0xbf7b0000,0xbf7b0000,0x3e483f80,
0x3f0e3f6d,0x3f55bec4,0x3f55bec4,0xbf0ebf6d,0xbf55bf35,0xbf0e3f35,0xbf0e3f35,0x3f553f35,0x3f7b3ec4,0x3e48bf6d,0x3e48bf6d,0xbf7bbec4,
0x3f750000,0xbe95bf80,0xbf62bf35,0xbef13f35,0xbf223f0e,0x3f463f55,0x3f7f3e48,0xbdc9bf7b,0x3dc9bf6d,0xbf7fbec4,0xbf463ec4,0x3f223f6d,
0x3ef13f7b,0x3f62be48,0x3e95bf55,0xbf75bf0e,0x3ec43f80,0x3f6d0000,0xbec4bf80,0xbf6d0000,0xbf6dbf35,0xbec43f35,0x3f6d3f35,0x3ec4bf35,
0x3f6d0000,0xbec4bf80,0xbf6d0000,0x3ec43f80,0xbec43f35,0x3f6d3f35,0x3ec4bf35,0xbf6dbf35,0xbf620000,0x3ef13f80,0x3e95bf35,0xbf75bf35,
0x3dc9bf55,0xbf7fbf0e,0x3f223f7b,0x3f46be48,0x3f463f6d,0x3f22bec4,0xbf7fbec4,0x3dc93f6d,0xbf75be48,0x3e953f7b,0x3ef1bf0e,0xbf62bf55,
0xbf0ebf80,0xbf550000,0x3f550000,0xbf0ebf80,0x3f7b3ec4,0xbe48bf6d,0x3e483f6d,0x3f7b3ec4,0xbe483f35,0x3f7b3f35,0xbf7bbf35,0xbe483f35,
0xbf55bf6d,0xbf0e3ec4,0x3f0ebec4,0xbf55bf6d,0x3f460000,0xbf22bf80,0x3f7f3f35,0x3dc9bf35,0x3ef13f7b,0x3f623e48,0xbe953f0e,0x3f753f55,
0xbf75bec4,0x3e953f6d,0xbf62bf6d,0xbef13ec4,0xbdc9bf55,0xbf7fbf0e,0x3f22be48,0xbf46bf7b,0x3f353f80,0x3f350000,0x3f353f80,0x3f350000,
0xbf350000,0x3f353f80,0xbf350000,0x3f353f80,0xbf35bf80,0xbf350000,0xbf35bf80,0xbf350000,0x3f350000,0xbf35bf80,0x3f350000,0xbf35bf80,
0xbf220000,0x3f463f80,0x3dc93f35,0x3f7f3f35,0xbf62bf7b,0xbef13e48,0xbf75bf0e,0x3e953f55,0x3e95bec4,0xbf75bf6d,0xbef1bf6d,0xbf62bec4,
0x3f7f3f55,0x3dc9bf0e,0x3f463e48,0xbf22bf7b,0xbf55bf80,0xbf0e0000,0xbf0e0000,0x3f553f80,0x3e48bec4,0xbf7bbf6d,0xbf7bbf6d,0xbe483ec4,
0x3f7b3f35,0xbe48bf35,0xbe48bf35,0xbf7bbf35,0x3f0e3f6d,0x3f553ec4,0x3f553ec4,0xbf0ebf6d,0x3ef10000,0xbf62bf80,0xbf75bf35,0x3e953f35,
0x3f7f3f55,0xbdc9bf0e,0xbf46bf7b,0xbf22be48,0x3f223f6d,0x3f463ec4,0x3dc9bec4,0xbf7fbf6d,0xbe953e48,0x3f753f7b,0x3f623f0e,0xbef1bf55,
0x3f6d3f80,0x3ec40000,0xbf6dbf80,0xbec40000,0x3ec43f35,0x3f6d3f35,0xbec4bf35,0xbf6dbf35,0xbec40000,0x3f6d3f80,0x3ec40000,0xbf6dbf80,
0xbf6dbf35,0x3ec43f35,0x3f6d3f35,0xbec4bf35,0xbe950000,0x3f753f80,0xbef1bf35,0xbf62bf35,0xbf46bf0e,0x3f223f55,0x3dc9be48,0xbf7fbf7b,
0xbf7fbf6d,0x3dc93ec4,0x3f223ec4,0xbf46bf6d,0xbf62bf7b,0xbef1be48,0x3f753f55,0xbe95bf0e,0xbf7bbf80,0xbe480000,0x3e480000,0xbf7bbf80,
0xbf55bf6d,0xbf0ebec4,0x3f0e3ec4,0xbf55bf6d,0xbf0ebf35,0xbf55bf35,0x3f553f35,0xbf0ebf35,0xbe48bec4,0xbf7bbf6d,0x3f7b3f6d,0xbe48bec4,
0x3dc90000,0xbf7fbf80,0x3f463f35,0xbf22bf35,0x3e953e48,0xbf75bf7b,0x3f623f55,0xbef1bf0e,0x3ef13ec4,0xbf62bf6d,0x3f753f6d,0xbe95bec4,
0x3f223f0e,0xbf46bf55,0x3f7f3f7b,0xbdc9be48,
};
__device__ __align__(128) const uint32_t T_F32[1024] = {
0x3f803f80,0x0,0x3f803f80,0x0,0x3f803f80,0x0,0x3f803f80,0x0,0x3f803f80,0x0,0x3f803f80,0x0,
0x3f803f80,0x0,0x3f803f80,0x0,0x3f7b3f80,0xbe480000,0xbe480000,0xbf7bbf80,0x3f553f6d,0xbf0ebec4,0xbf0ebec4,0xbf55bf6d,
0x3f0e3f35,0xbf55bf35,0xbf55bf35,0xbf0ebf35,0x3e483ec4,0xbf7bbf6d,0xbf7bbf6d,0xbe48bec4,0x3f6d3f80,0xbec40000,0xbf6dbf80,0x3ec40000,
0x3ec43f35,0xbf6dbf35,0xbec4bf35,0x3f6d3f35,0xbec40000,0xbf6dbf80,0x3ec40000,0x3f6d3f80,0xbf6dbf35,0xbec4bf35,0x3f6d3f35,0x3ec43f35,
0x3f553f80,0xbf0e0000,0x3f0e0000,0x3f553f80,0xbe483ec4,0xbf7bbf6d,0x3f7b3f6d,0xbe483ec4,0xbf7bbf35,0xbe48bf35,0x3e483f35,0xbf7bbf35,
0xbf0ebf6d,0x3f553ec4,0xbf55bec4,0xbf0ebf6d,0x3f353f80,0xbf350000,0x3f353f80,0xbf350000,0xbf350000,0xbf35bf80,0xbf350000,0xbf35bf80,
0xbf35bf80,0x3f350000,0xbf35bf80,0x3f350000,0x3f350000,0x3f353f80,0x3f350000,0x3f353f80,0x3f0e3f80,0xbf550000,0xbf550000,0xbf0ebf80,
0xbf7bbec4,0xbe48bf6d,0xbe48bf6d,0x3f7b3ec4,0x3e48bf35,0x3f7b3f35,0x3f7b3f35,0xbe483f35,0x3f553f6d,0xbf0e3ec4,0xbf0e3ec4,0xbf55bf6d,
0x3ec43f80,0xbf6d0000,0xbec4bf80,0x3f6d0000,0xbf6dbf35,0x3ec4bf35,0x3f6d3f35,0xbec43f35,0x3f6d0000,0x3ec43f80,0xbf6d0000,0xbec4bf80,
0xbec43f35,0xbf6dbf35,0x3ec4bf35,0x3f6d3f35,0x3e483f80,0xbf7b0000,0x3f7b0000,0x3e483f80,0xbf0ebf6d,0x3f55bec4,0xbf553ec4,0xbf0ebf6d,
0x3f553f35,0xbf0e3f35,0x3f0ebf35,0x3f553f35,0xbf7bbec4,0x3e48bf6d,0xbe483f6d,0xbf7bbec4,0x3f80,0xbf800000,0x3f80,0xbf800000,
0xbf80,0x3f800000,0xbf80,0x3f800000,0x3f80,0xbf800000,0x3f80,0xbf800000,0xbf80,0x3f800000,0xbf80,0x3f800000,
0xbe483f80,0xbf7b0000,0xbf7b0000,0x3e48bf80,0x3f0ebf6d,0x3f553ec4,0x3f553ec4,0xbf0e3f6d,0xbf553f35,0xbf0ebf35,0xbf0ebf35,0x3f55bf35,
0x3f7bbec4,0x3e483f6d,0x3e483f6d,0xbf7b3ec4,0xbec43f80,0xbf6d0000,0x3ec4bf80,0x3f6d0000,0x3f6dbf35,0x3ec43f35,0xbf6d3f35,0xbec4bf35,
0xbf6d0000,0x3ec4bf80,0x3f6d0000,0xbec43f80,0x3ec43f35,0xbf6d3f35,0xbec4bf35,0x3f6dbf35,0xbf0e3f80,0xbf550000,0x3f550000,0xbf0e3f80,
0x3f7bbec4,0xbe483f6d,0x3e48bf6d,0x3f7bbec4,0xbe48bf35,0x3f7bbf35,0xbf7b3f35,0xbe48bf35,0xbf553f6d,0xbf0ebec4,0x3f0e3ec4,0xbf553f6d,
0xbf353f80,0xbf350000,0xbf353f80,0xbf350000,0x3f350000,0xbf353f80,0x3f350000,0xbf353f80,0x3f35bf80,0x3f350000,0x3f35bf80,0x3f350000,
0xbf350000,0x3f35bf80,0xbf350000,0x3f35bf80,0xbf553f80,0xbf0e0000,0xbf0e0000,0x3f55bf80,0x3e483ec4,0xbf7b3f6d,0xbf7b3f6d,0xbe48bec4,
0x3f7bbf35,0xbe483f35,0xbe483f35,0xbf7b3f35,0x3f0ebf6d,0x3f55bec4,0x3f55bec4,0xbf0e3f6d,0xbf6d3f80,0xbec40000,0x3f6dbf80,0x3ec40000,
0xbec43f35,0xbf6d3f35,0x3ec4bf35,0x3f6dbf35,0x3ec40000,0xbf6d3f80,0xbec40000,0x3f6dbf80,0x3f6dbf35,0xbec43f35,0xbf6d3f35,0x3ec4bf35,
0xbf7b3f80,0xbe480000,0x3e480000,0xbf7b3f80,0xbf553f6d,0xbf0e3ec4,0x3f0ebec4,0xbf553f6d,0xbf0e3f35,0xbf553f35,0x3f55bf35,0xbf0e3f35,
0xbe483ec4,0xbf7b3f6d,0x3f7bbf6d,0xbe483ec4,0xbf803f80,0x0,0xbf803f80,0x0,0xbf803f80,0x0,0xbf803f80,0x0,
0xbf803f80,0x0,0xbf803f80,0x0,0xbf803f80,0x0,0xbf803f80,0x0,0xbf7b3f80,0x3e480000,0x3e480000,0x3f7bbf80,
0xbf553f6d,0x3f0ebec4,0x3f0ebec4,0x3f55bf6d,0xbf0e3f35,0x3f55bf35,0x3f55bf35,0x3f0ebf35,0xbe483ec4,0x3f7bbf6d,0x3f7bbf6d,0x3e48bec4,
0xbf6d3f80,0x3ec40000,0x3f6dbf80,0xbec40000,0xbec43f35,0x3f6dbf35,0x3ec4bf35,0xbf6d3f35,0x3ec40000,0x3f6dbf80,0xbec40000,0xbf6d3f80,
0x3f6dbf35,0x3ec4bf35,0xbf6d3f35,0xbec43f35,0xbf553f80,0x3f0e0000,0xbf0e0000,0xbf553f80,0x3e483ec4,0x3f7bbf6d,0xbf7b3f6d,0x3e483ec4,
0x3f7bbf35,0x3e48bf35,0xbe483f35,0x3f7bbf35,0x3f0ebf6d,0xbf553ec4,0x3f55bec4,0x3f0ebf6d,0xbf353f80,0x3f350000,0xbf353f80,0x3f350000,
0x3f350000,0x3f35bf80,0x3f350000,0x3f35bf80,0x3f35bf80,0xbf350000,0x3f35bf80,0xbf350000,0xbf350000,0xbf353f80,0xbf350000,0xbf353f80,
0xbf0e3f80,0x3f550000,0x3f550000,0x3f0ebf80,0x3f7bbec4,0x3e48bf6d,0x3e48bf6d,0xbf7b3ec4,0xbe48bf35,0xbf7b3f35,0xbf7b3f35,0x3e483f35,
0xbf553f6d,0x3f0e3ec4,0x3f0e3ec4,0x3f55bf6d,0xbec43f80,0x3f6d0000,0x3ec4bf80,0xbf6d0000,0x3f6dbf35,0xbec4bf35,0xbf6d3f35,0x3ec43f35,
0xbf6d0000,0xbec43f80,0x3f6d0000,0x3ec4bf80,0x3ec43f35,0x3f6dbf35,0xbec4bf35,0xbf6d3f35,0xbe483f80,0x3f7b0000,0xbf7b0000,0xbe483f80,
0x3f0ebf6d,0xbf55bec4,0x3f553ec4,0x3f0ebf6d,0xbf553f35,0x3f0e3f35,0xbf0ebf35,0xbf553f35,0x3f7bbec4,0xbe48bf6d,0x3e483f6d,0x3f7bbec4,
0x3f80,0x3f800000,0x3f80,0x3f800000,0xbf80,0xbf800000,0xbf80,0xbf800000,0x3f80,0x3f800000,0x3f80,0x3f800000,
0xbf80,0xbf800000,0xbf80,0xbf800000,0x3e483f80,0x3f7b0000,0x3f7b0000,0xbe48bf80,0xbf0ebf6d,0xbf553ec4,0xbf553ec4,0x3f0e3f6d,
0x3f553f35,0x3f0ebf35,0x3f0ebf35,0xbf55bf35,0xbf7bbec4,0xbe483f6d,0xbe483f6d,0x3f7b3ec4,0x3ec43f80,0x3f6d0000,0xbec4bf80,0xbf6d0000,
0xbf6dbf35,0xbec43f35,0x3f6d3f35,0x3ec4bf35,0x3f6d0000,0xbec4bf80,0xbf6d0000,0x3ec43f80,0xbec43f35,0x3f6d3f35,0x3ec4bf35,0xbf6dbf35,
0x3f0e3f80,0x3f550000,0xbf550000,0x3f0e3f80,0xbf7bbec4,0x3e483f6d,0xbe48bf6d,0xbf7bbec4,0x3e48bf35,0xbf7bbf35,0x3f7b3f35,0x3e48bf35,
0x3f553f6d,0x3f0ebec4,0xbf0e3ec4,0x3f553f6d,0x3f353f80,0x3f350000,0x3f353f80,0x3f350000,0xbf350000,0x3f353f80,0xbf350000,0x3f353f80,
0xbf35bf80,0xbf350000,0xbf35bf80,0xbf350000,0x3f350000,0xbf35bf80,0x3f350000,0xbf35bf80,0x3f553f80,0x3f0e0000,0x3f0e0000,0xbf55bf80,
0xbe483ec4,0x3f7b3f6d,0x3f7b3f6d,0x3e48bec4,0xbf7bbf35,0x3e483f35,0x3e483f35,0x3f7b3f35,0xbf0ebf6d,0xbf55bec4,0xbf55bec4,0x3f0e3f6d,
0x3f6d3f80,0x3ec40000,0xbf6dbf80,0xbec40000,0x3ec43f35,0x3f6d3f35,0xbec4bf35,0xbf6dbf35,0xbec40000,0x3f6d3f80,0x3ec40000,0xbf6dbf80,
0xbf6dbf35,0x3ec43f35,0x3f6d3f35,0xbec4bf35,0x3f7b3f80,0x3e480000,0xbe480000,0x3f7b3f80,0x3f553f6d,0x3f0e3ec4,0xbf0ebec4,0x3f553f6d,
0x3f0e3f35,0x3f553f35,0xbf55bf35,0x3f0e3f35,0x3e483ec4,0x3f7b3f6d,0xbf7bbf6d,0x3e483ec4,0x3f803f80,0x0,0x3f803f80,0x0,
0x3f803f80,0x0,0x3f803f80,0x0,0x3f803f80,0x0,0x3f803f80,0x0,0x3f803f80,0x0,0x3f803f80,0x0,
0xbf7bbf80,0x3e480000,0x3e480000,0x3f7b3f80,0xbf55bf6d,0x3f0e3ec4,0x3f0e3ec4,0x3f553f6d,0xbf0ebf35,0x3f553f35,0x3f553f35,0x3f0e3f35,
0xbe48bec4,0x3f7b3f6d,0x3f7b3f6d,0x3e483ec4,0x3f6d3f80,0xbec40000,0xbf6dbf80,0x3ec40000,0x3ec43f35,0xbf6dbf35,0xbec4bf35,0x3f6d3f35,
0xbec40000,0xbf6dbf80,0x3ec40000,0x3f6d3f80,0xbf6dbf35,0xbec4bf35,0x3f6d3f35,0x3ec43f35,0xbf55bf80,0x3f0e0000,0xbf0e0000,0xbf55bf80,
0x3e48bec4,0x3f7b3f6d,0xbf7bbf6d,0x3e48bec4,0x3f7b3f35,0x3e483f35,0xbe48bf35,0x3f7b3f35,0x3f0e3f6d,0xbf55bec4,0x3f553ec4,0x3f0e3f6d,
0x3f353f80,0xbf350000,0x3f353f80,0xbf350000,0xbf350000,0xbf35bf80,0xbf350000,0xbf35bf80,0xbf35bf80,0x3f350000,0xbf35bf80,0x3f350000,
0x3f350000,0x3f353f80,0x3f350000,0x3f353f80,0xbf0ebf80,0x3f550000,0x3f550000,0x3f0e3f80,0x3f7b3ec4,0x3e483f6d,0x3e483f6d,0xbf7bbec4,
0xbe483f35,0xbf7bbf35,0xbf7bbf35,0x3e48bf35,0xbf55bf6d,0x3f0ebec4,0x3f0ebec4,0x3f553f6d,0x3ec43f80,0xbf6d0000,0xbec4bf80,0x3f6d0000,
0xbf6dbf35,0x3ec4bf35,0x3f6d3f35,0xbec43f35,0x3f6d0000,0x3ec43f80,0xbf6d0000,0xbec4bf80,0xbec43f35,0xbf6dbf35,0x3ec4bf35,0x3f6d3f35,
0xbe48bf80,0x3f7b0000,0xbf7b0000,0xbe48bf80,0x3f0e3f6d,0xbf553ec4,0x3f55bec4,0x3f0e3f6d,0xbf55bf35,0x3f0ebf35,0xbf0e3f35,0xbf55bf35,
0x3f7b3ec4,0xbe483f6d,0x3e48bf6d,0x3f7b3ec4,0x3f80,0xbf800000,0x3f80,0xbf800000,0xbf80,0x3f800000,0xbf80,0x3f800000,
0x3f80,0xbf800000,0x3f80,0xbf800000,0xbf80,0x3f800000,0xbf80,0x3f800000,0x3e48bf80,0x3f7b0000,0x3f7b0000,0xbe483f80,
0xbf0e3f6d,0xbf55bec4,0xbf55bec4,0x3f0ebf6d,0x3f55bf35,0x3f0e3f35,0x3f0e3f35,0xbf553f35,0xbf7b3ec4,0xbe48bf6d,0xbe48bf6d,0x3f7bbec4,
0xbec43f80,0xbf6d0000,0x3ec4bf80,0x3f6d0000,0x3f6dbf35,0x3ec43f35,0xbf6d3f35,0xbec4bf35,0xbf6d0000,0x3ec4bf80,0x3f6d0000,0xbec43f80,
0x3ec43f35,0xbf6d3f35,0xbec4bf35,0x3f6dbf35,0x3f0ebf80,0x3f550000,0xbf550000,0x3f0ebf80,0xbf7b3ec4,0x3e48bf6d,0xbe483f6d,0xbf7b3ec4,
0x3e483f35,0xbf7b3f35,0x3f7bbf35,0x3e483f35,0x3f55bf6d,0x3f0e3ec4,0xbf0ebec4,0x3f55bf6d,0xbf353f80,0xbf350000,0xbf353f80,0xbf350000,
0x3f350000,0xbf353f80,0x3f350000,0xbf353f80,0x3f35bf80,0x3f350000,0x3f35bf80,0x3f350000,0xbf350000,0x3f35bf80,0xbf350000,0x3f35bf80,
0x3f55bf80,0x3f0e0000,0x3f0e0000,0xbf553f80,0xbe48bec4,0x3f7bbf6d,0x3f7bbf6d,0x3e483ec4,0xbf7b3f35,0x3e48bf35,0x3e48bf35,0x3f7bbf35,
0xbf0e3f6d,0xbf553ec4,0xbf553ec4,0x3f0ebf6d,0xbf6d3f80,0xbec40000,0x3f6dbf80,0x3ec40000,0xbec43f35,0xbf6d3f35,0x3ec4bf35,0x3f6dbf35,
0x3ec40000,0xbf6d3f80,0xbec40000,0x3f6dbf80,0x3f6dbf35,0xbec43f35,0xbf6d3f35,0x3ec4bf35,0x3f7bbf80,0x3e480000,0xbe480000,0x3f7bbf80,
0x3f55bf6d,0x3f0ebec4,0xbf0e3ec4,0x3f55bf6d,0x3f0ebf35,0x3f55bf35,0xbf553f35,0x3f0ebf35,0x3e48bec4,0x3f7bbf6d,0xbf7b3f6d,0x3e48bec4,
0xbf803f80,0x0,0xbf803f80,0x0,0xbf803f80,0x0,0xbf803f80,0x0,0xbf803f80,0x0,0xbf803f80,0x0,
0xbf803f80,0x0,0xbf803f80,0x0,0x3f7bbf80,0xbe480000,0xbe480000,0xbf7b3f80,0x3f55bf6d,0xbf0e3ec4,0xbf0e3ec4,0xbf553f6d,
0x3f0ebf35,0xbf553f35,0xbf553f35,0xbf0e3f35,0x3e48bec4,0xbf7b3f6d,0xbf7b3f6d,0xbe483ec4,0xbf6d3f80,0x3ec40000,0x3f6dbf80,0xbec40000,
0xbec43f35,0x3f6dbf35,0x3ec4bf35,0xbf6d3f35,0x3ec40000,0x3f6dbf80,0xbec40000,0xbf6d3f80,0x3f6dbf35,0x3ec4bf35,0xbf6d3f35,0xbec43f35,
0x3f55bf80,0xbf0e0000,0x3f0e0000,0x3f55bf80,0xbe48bec4,0xbf7b3f6d,0x3f7bbf6d,0xbe48bec4,0xbf7b3f35,0xbe483f35,0x3e48bf35,0xbf7b3f35,
0xbf0e3f6d,0x3f55bec4,0xbf553ec4,0xbf0e3f6d,0xbf353f80,0x3f350000,0xbf353f80,0x3f350000,0x3f350000,0x3f35bf80,0x3f350000,0x3f35bf80,
0x3f35bf80,0xbf350000,0x3f35bf80,0xbf350000,0xbf350000,0xbf353f80,0xbf350000,0xbf353f80,0x3f0ebf80,0xbf550000,0xbf550000,0xbf0e3f80,
0xbf7b3ec4,0xbe483f6d,0xbe483f6d,0x3f7bbec4,0x3e483f35,0x3f7bbf35,0x3f7bbf35,0xbe48bf35,0x3f55bf6d,0xbf0ebec4,0xbf0ebec4,0xbf553f6d,
0xbec43f80,0x3f6d0000,0x3ec4bf80,0xbf6d0000,0x3f6dbf35,0xbec4bf35,0xbf6d3f35,0x3ec43f35,0xbf6d0000,0xbec43f80,0x3f6d0000,0x3ec4bf80,
0x3ec43f35,0x3f6dbf35,0xbec4bf35,0xbf6d3f35,0x3e48bf80,0xbf7b0000,0x3f7b0000,0x3e48bf80,0xbf0e3f6d,0x3f553ec4,0xbf55bec4,0xbf0e3f6d,
0x3f55bf35,0xbf0ebf35,0x3f0e3f35,0x3f55bf35,0xbf7b3ec4,0x3e483f6d,0xbe48bf6d,0xbf7b3ec4,0x3f80,0x3f800000,0x3f80,0x3f800000,
0xbf80,0xbf800000,0xbf80,0xbf800000,0x3f80,0x3f800000,0x3f80,0x3f800000,0xbf80,0xbf800000,0xbf80,0xbf800000,
0xbe48bf80,0xbf7b0000,0xbf7b0000,0x3e483f80,0x3f0e3f6d,0x3f55bec4,0x3f55bec4,0xbf0ebf6d,0xbf55bf35,0xbf0e3f35,0xbf0e3f35,0x3f553f35,
0x3f7b3ec4,0x3e48bf6d,0x3e48bf6d,0xbf7bbec4,0x3ec43f80,0x3f6d0000,0xbec4bf80,0xbf6d0000,0xbf6dbf35,0xbec43f35,0x3f6d3f35,0x3ec4bf35,
0x3f6d0000,0xbec4bf80,0xbf6d0000,0x3ec43f80,0xbec43f35,0x3f6d3f35,0x3ec4bf35,0xbf6dbf35,0xbf0ebf80,0xbf550000,0x3f550000,0xbf0ebf80,
0x3f7b3ec4,0xbe48bf6d,0x3e483f6d,0x3f7b3ec4,0xbe483f35,0x3f7b3f35,0xbf7bbf35,0xbe483f35,0xbf55bf6d,0xbf0e3ec4,0x3f0ebec4,0xbf55bf6d,
0x3f353f80,0x3f350000,0x3f353f80,0x3f350000,0xbf350000,0x3f353f80,0xbf350000,0x3f353f80,0xbf35bf80,0xbf350000,0xbf35bf80,0xbf350000,
0x3f350000,0xbf35bf80,0x3f350000,0xbf35bf80,0xbf55bf80,0xbf0e0000,0xbf0e0000,0x3f553f80,0x3e48bec4,0xbf7bbf6d,0xbf7bbf6d,0xbe483ec4,
0x3f7b3f35,0xbe48bf35,0xbe48bf35,0xbf7bbf35,0x3f0e3f6d,0x3f553ec4,0x3f553ec4,0xbf0ebf6d,0x3f6d3f80,0x3ec40000,0xbf6dbf80,0xbec40000,
0x3ec43f35,0x3f6d3f35,0xbec4bf35,0xbf6dbf35,0xbec40000,0x3f6d3f80,0x3ec40000,0xbf6dbf80,0xbf6dbf35,0x3ec43f35,0x3f6d3f35,0xbec4bf35,
0xbf7bbf80,0xbe480000,0x3e480000,0xbf7bbf80,0xbf55bf6d,0xbf0ebec4,0x3f0e3ec4,0xbf55bf6d,0xbf0ebf35,0xbf55bf35,0x3f553f35,0xbf0ebf35,
0xbe48bec4,0xbf7bbf6d,0x3f7b3f6d,0xbe48bec4,
};
__device__ __align__(128) const uint32_t T_G[4096] = {
0x80003f80,0x80003f80,0x80003f80,0x80003f80,0x80003f80,0x80003f80,0x80003f80,0x80003f80,0x80003f80,0x80003f80,0x80003f80,0x80003f80,
0x80003f80,0x80003f80,0x80003f80,0x80003f80,0x80003f80,0x80003f80,0x80003f80,0x80003f80,0x80003f80,0x80003f80,0x80003f80,0x80003f80,
0x80003f80,0x80003f80,0x80003f80,0x80003f80,0x80003f80,0x80003f80,0x80003f80,0x80003f80,0x3f800000,0x3f800000,0x3f800000,0x3f800000,
0x3f800000,0x3f800000,0x3f800000,0x3f800000,0x3f800000,0x3f800000,0x3f800000,0x3f800000,0x3f800000,0x3f800000,0x3f800000,0x3f800000,
0x3f800000,0x3f800000,0x3f800000,0x3f800000,0x3f800000,0x3f800000,0x3f800000,0x3f800000,0x3f800000,0x3f800000,0x3f800000,0x3f800000,
0x3f800000,0x3f800000,0x3f800000,0x3f800000,0x3f800000,0x3f7bbe48,0x3f6dbec4,0x3f55bf0e,0x3f35bf35,0x3f0ebf55,0x3ec4bf6d,0x3e48bf7b,
0x80003f80,0x3e483f7b,0x3ec43f6d,0x3f0e3f55,0x3f353f35,0x3f553f0e,0x3f6d3ec4,0x3f7b3e48,0xbf800000,0xbf7b3e48,0xbf6d3ec4,0xbf553f0e,
0xbf353f35,0xbf0e3f55,0xbec43f6d,0xbe483f7b,0x8000bf80,0xbe48bf7b,0xbec4bf6d,0xbf0ebf55,0xbf35bf35,0xbf55bf0e,0xbf6dbec4,0xbf7bbe48,
0xbf35bf35,0xbf55bf0e,0xbf6dbec4,0xbf7bbe48,0xbf80,0xbe48bf7b,0xbec4bf6d,0xbf0ebf55,0x3f35bf35,0x3f0ebf55,0x3ec4bf6d,0x3e48bf7b,
0x3f800000,0x3f7bbe48,0x3f6dbec4,0x3f55bf0e,0x3f353f35,0x3f553f0e,0x3f6d3ec4,0x3f7b3e48,0x3f80,0x3e483f7b,0x3ec43f6d,0x3f0e3f55,
0xbf353f35,0xbf0e3f55,0xbec43f6d,0xbe483f7b,0xbf800000,0xbf7b3e48,0xbf6d3ec4,0xbf553f0e,0x80003f80,0x3ec43f6d,0x3f353f35,0x3f6d3ec4,
0x3f800000,0x3f6dbec4,0x3f35bf35,0x3ec4bf6d,0x8000bf80,0xbec4bf6d,0xbf35bf35,0xbf6dbec4,0xbf800000,0xbf6d3ec4,0xbf353f35,0xbec43f6d,
0x80003f80,0x3ec43f6d,0x3f353f35,0x3f6d3ec4,0x3f800000,0x3f6dbec4,0x3f35bf35,0x3ec4bf6d,0x8000bf80,0xbec4bf6d,0xbf35bf35,0xbf6dbec4,
0xbf800000,0xbf6d3ec4,0xbf353f35,0xbec43f6d,0xbf80,0xbec4bf6d,0xbf35bf35,0xbf6dbec4,0x3f800000,0x3f6dbec4,0x3f35bf35,0x3ec4bf6d,
0x3f80,0x3ec43f6d,0x3f353f35,0x3f6d3ec4,0xbf800000,0xbf6d3ec4,0xbf353f35,0xbec43f6d,0xbf80,0xbec4bf6d,0xbf35bf35,0xbf6dbec4,
0x3f800000,0x3f6dbec4,0x3f35bf35,0x3ec4bf6d,0x3f80,0x3ec43f6d,0x3f353f35,0x3f6d3ec4,0xbf800000,0xbf6d3ec4,0xbf353f35,0xbec43f6d,
0x3f800000,0x3f55bf0e,0x3ec4bf6d,0xbe48bf7b,0xbf35bf35,0xbf7bbe48,0xbf6d3ec4,0xbf0e3f55,0x8000bf80,0xbf0ebf55,0xbf6dbec4,0xbf7b3e48,
0xbf353f35,0xbe483f7b,0x3ec43f6d,0x3f553f0e,0xbf800000,0xbf553f0e,0xbec43f6d,0x3e483f7b,0x3f353f35,0x3f7b3e48,0x3f6dbec4,0x3f0ebf55,
0x80003f80,0x3f0e3f55,0x3f6d3ec4,0x3f7bbe48,0x3f35bf35,0x3e48bf7b,0xbec4bf6d,0xbf55bf0e,0xbf353f35,0xbe483f7b,0x3ec43f6d,0x3f553f0e,
0xbf80,0xbf0ebf55,0xbf6dbec4,0xbf7b3e48,0x3f353f35,0x3f7b3e48,0x3f6dbec4,0x3f0ebf55,0xbf800000,0xbf553f0e,0xbec43f6d,0x3e483f7b,
0x3f35bf35,0x3e48bf7b,0xbec4bf6d,0xbf55bf0e,0x3f80,0x3f0e3f55,0x3f6d3ec4,0x3f7bbe48,0xbf35bf35,0xbf7bbe48,0xbf6d3ec4,0xbf0e3f55,
0x3f800000,0x3f55bf0e,0x3ec4bf6d,0xbe48bf7b,0x80003f80,0x3f353f35,0x3f800000,0x3f35bf35,0x8000bf80,0xbf35bf35,0xbf800000,0xbf353f35,
0x80003f80,0x3f353f35,0x3f800000,0x3f35bf35,0x8000bf80,0xbf35bf35,0xbf800000,0xbf353f35,0x80003f80,0x3f353f35,0x3f800000,0x3f35bf35,
0x8000bf80,0xbf35bf35,0xbf800000,0xbf353f35,0x80003f80,0x3f353f35,0x3f800000,0x3f35bf35,0x8000bf80,0xbf35bf35,0xbf800000,0xbf353f35,
0xbf800000,0xbf353f35,0x3f80,0x3f353f35,0x3f800000,0x3f35bf35,0xbf80,0xbf35bf35,0xbf800000,0xbf353f35,0x3f80,0x3f353f35,
0x3f800000,0x3f35bf35,0xbf80,0xbf35bf35,0xbf800000,0xbf353f35,0x3f80,0x3f353f35,0x3f800000,0x3f35bf35,0xbf80,0xbf35bf35,
0xbf800000,0xbf353f35,0x3f80,0x3f353f35,0x3f800000,0x3f35bf35,0xbf80,0xbf35bf35,0x3f800000,0x3f0ebf55,0xbec4bf6d,0xbf7bbe48,
0xbf353f35,0x3e483f7b,0x3f6d3ec4,0x3f55bf0e,0x80003f80,0x3f553f0e,0x3f6dbec4,0x3e48bf7b,0xbf35bf35,0xbf7b3e48,0xbec43f6d,0x3f0e3f55,
0xbf800000,0xbf0e3f55,0x3ec43f6d,0x3f7b3e48,0x3f35bf35,0xbe48bf7b,0xbf6dbec4,0xbf553f0e,0x8000bf80,0xbf55bf0e,0xbf6d3ec4,0xbe483f7b,
0x3f353f35,0x3f7bbe48,0x3ec4bf6d,0xbf0ebf55,0x3f353f35,0x3f7bbe48,0x3ec4bf6d,0xbf0ebf55,0xbf80,0xbf55bf0e,0xbf6d3ec4,0xbe483f7b,
0xbf353f35,0x3e483f7b,0x3f6d3ec4,0x3f55bf0e,0x3f800000,0x3f0ebf55,0xbec4bf6d,0xbf7bbe48,0xbf35bf35,0xbf7b3e48,0xbec43f6d,0x3f0e3f55,
0x3f80,0x3f553f0e,0x3f6dbec4,0x3e48bf7b,0x3f35bf35,0xbe48bf7b,0xbf6dbec4,0xbf553f0e,0xbf800000,0xbf0e3f55,0x3ec43f6d,0x3f7b3e48,
0x80003f80,0x3f6d3ec4,0x3f35bf35,0xbec4bf6d,0xbf800000,0xbec43f6d,0x3f353f35,0x3f6dbec4,0x8000bf80,0xbf6dbec4,0xbf353f35,0x3ec43f6d,
0x3f800000,0x3ec4bf6d,0xbf35bf35,0xbf6d3ec4,0x80003f80,0x3f6d3ec4,0x3f35bf35,0xbec4bf6d,0xbf800000,0xbec43f6d,0x3f353f35,0x3f6dbec4,
0x8000bf80,0xbf6dbec4,0xbf353f35,0x3ec43f6d,0x3f800000,0x3ec4bf6d,0xbf35bf35,0xbf6d3ec4,0x3f80,0x3f6d3ec4,0x3f35bf35,0xbec4bf6d,
0x3f800000,0x3ec4bf6d,0xbf35bf35,0xbf6d3ec4,0xbf80,0xbf6dbec4,0xbf353f35,0x3ec43f6d,0xbf800000,0xbec43f6d,0x3f353f35,0x3f6dbec4,
0x3f80,0x3f6d3ec4,0x3f35bf35,0xbec4bf6d,0x3f800000,0x3ec4bf6d,0xbf35bf35,0xbf6d3ec4,0xbf80,0xbf6dbec4,0xbf353f35,0x3ec43f6d,
0xbf800000,0xbec43f6d,0x3f353f35,0x3f6dbec4,0x3f800000,0x3e48bf7b,0xbf6dbec4,0xbf0e3f55,0x3f353f35,0x3f55bf0e,0xbec4bf6d,0xbf7b3e48,
0x8000bf80,0xbf7bbe48,0xbec43f6d,0x3f553f0e,0x3f35bf35,0xbf0ebf55,0xbf6d3ec4,0x3e483f7b,0xbf800000,0xbe483f7b,0x3f6d3ec4,0x3f0ebf55,
0xbf35bf35,0xbf553f0e,0x3ec43f6d,0x3f7bbe48,0x80003f80,0x3f7b3e48,0x3ec4bf6d,0xbf55bf0e,0xbf353f35,0x3f0e3f55,0x3f6dbec4,0xbe48bf7b,
0x3f35bf35,0xbf0ebf55,0xbf6d3ec4,0x3e483f7b,0xbf80,0xbf7bbe48,0xbec43f6d,0x3f553f0e,0xbf35bf35,0xbf553f0e,0x3ec43f6d,0x3f7bbe48,
0xbf800000,0xbe483f7b,0x3f6d3ec4,0x3f0ebf55,0xbf353f35,0x3f0e3f55,0x3f6dbec4,0xbe48bf7b,0x3f80,0x3f7b3e48,0x3ec4bf6d,0xbf55bf0e,
0x3f353f35,0x3f55bf0e,0xbec4bf6d,0xbf7b3e48,0x3f800000,0x3e48bf7b,0xbf6dbec4,0xbf0e3f55,0x80003f80,0x3f800000,0x8000bf80,0xbf800000,
0x80003f80,0x3f800000,0x8000bf80,0xbf800000,0x80003f80,0x3f800000,0x8000bf80,0xbf800000,0x80003f80,0x3f800000,0x8000bf80,0xbf800000,
0x80003f80,0x3f800000,0x8000bf80,0xbf800000,0x80003f80,0x3f800000,0x8000bf80,0xbf800000,0x80003f80,0x3f800000,0x8000bf80,0xbf800000,
0x80003f80,0x3f800000,0x8000bf80,0xbf800000,0x3f800000,0xbf80,0xbf800000,0x3f80,0x3f800000,0xbf80,0xbf800000,0x3f80,
0x3f800000,0xbf80,0xbf800000,0x3f80,0x3f800000,0xbf80,0xbf800000,0x3f80,0x3f800000,0xbf80,0xbf800000,0x3f80,
0x3f800000,0xbf80,0xbf800000,0x3f80,0x3f800000,0xbf80,0xbf800000,0x3f80,0x3f800000,0xbf80,0xbf800000,0x3f80,
0x3f800000,0xbe48bf7b,0xbf6d3ec4,0x3f0e3f55,0x3f35bf35,0xbf55bf0e,0xbec43f6d,0x3f7b3e48,0x80003f80,0x3f7bbe48,0xbec4bf6d,0xbf553f0e,
0x3f353f35,0x3f0ebf55,0xbf6dbec4,0xbe483f7b,0xbf800000,0x3e483f7b,0x3f6dbec4,0xbf0ebf55,0xbf353f35,0x3f553f0e,0x3ec4bf6d,0xbf7bbe48,
0x8000bf80,0xbf7b3e48,0x3ec43f6d,0x3f55bf0e,0xbf35bf35,0xbf0e3f55,0x3f6d3ec4,0x3e48bf7b,0xbf35bf35,0xbf0e3f55,0x3f6d3ec4,0x3e48bf7b,
0xbf80,0xbf7b3e48,0x3ec43f6d,0x3f55bf0e,0x3f35bf35,0xbf55bf0e,0xbec43f6d,0x3f7b3e48,0x3f800000,0xbe48bf7b,0xbf6d3ec4,0x3f0e3f55,
0x3f353f35,0x3f0ebf55,0xbf6dbec4,0xbe483f7b,0x3f80,0x3f7bbe48,0xbec4bf6d,0xbf553f0e,0xbf353f35,0x3f553f0e,0x3ec4bf6d,0xbf7bbe48,
0xbf800000,0x3e483f7b,0x3f6dbec4,0xbf0ebf55,0x80003f80,0x3f6dbec4,0xbf35bf35,0xbec43f6d,0x3f800000,0xbec4bf6d,0xbf353f35,0x3f6d3ec4,
0x8000bf80,0xbf6d3ec4,0x3f353f35,0x3ec4bf6d,0xbf800000,0x3ec43f6d,0x3f35bf35,0xbf6dbec4,0x80003f80,0x3f6dbec4,0xbf35bf35,0xbec43f6d,
0x3f800000,0xbec4bf6d,0xbf353f35,0x3f6d3ec4,0x8000bf80,0xbf6d3ec4,0x3f353f35,0x3ec4bf6d,0xbf800000,0x3ec43f6d,0x3f35bf35,0xbf6dbec4,
0xbf80,0xbf6d3ec4,0x3f353f35,0x3ec4bf6d,0x3f800000,0xbec4bf6d,0xbf353f35,0x3f6d3ec4,0x3f80,0x3f6dbec4,0xbf35bf35,0xbec43f6d,
0xbf800000,0x3ec43f6d,0x3f35bf35,0xbf6dbec4,0xbf80,0xbf6d3ec4,0x3f353f35,0x3ec4bf6d,0x3f800000,0xbec4bf6d,0xbf353f35,0x3f6d3ec4,
0x3f80,0x3f6dbec4,0xbf35bf35,0xbec43f6d,0xbf800000,0x3ec43f6d,0x3f35bf35,0xbf6dbec4,0x3f800000,0xbf0ebf55,0xbec43f6d,0x3f7bbe48,
0xbf35bf35,0xbe483f7b,0x3f6dbec4,0xbf55bf0e,0x8000bf80,0xbf553f0e,0x3f6d3ec4,0xbe48bf7b,0xbf353f35,0x3f7b3e48,0xbec4bf6d,0xbf0e3f55,
0xbf800000,0x3f0e3f55,0x3ec4bf6d,0xbf7b3e48,0x3f353f35,0x3e48bf7b,0xbf6d3ec4,0x3f553f0e,0x80003f80,0x3f55bf0e,0xbf6dbec4,0x3e483f7b,
0x3f35bf35,0xbf7bbe48,0x3ec43f6d,0x3f0ebf55,0xbf353f35,0x3f7b3e48,0xbec4bf6d,0xbf0e3f55,0xbf80,0xbf553f0e,0x3f6d3ec4,0xbe48bf7b,
0x3f353f35,0x3e48bf7b,0xbf6d3ec4,0x3f553f0e,0xbf800000,0x3f0e3f55,0x3ec4bf6d,0xbf7b3e48,0x3f35bf35,0xbf7bbe48,0x3ec43f6d,0x3f0ebf55,
0x3f80,0x3f55bf0e,0xbf6dbec4,0x3e483f7b,0xbf35bf35,0xbe483f7b,0x3f6dbec4,0xbf55bf0e,0x3f800000,0xbf0ebf55,0xbec43f6d,0x3f7bbe48,
0x80003f80,0x3f35bf35,0xbf800000,0x3f353f35,0x8000bf80,0xbf353f35,0x3f800000,0xbf35bf35,0x80003f80,0x3f35bf35,0xbf800000,0x3f353f35,
0x8000bf80,0xbf353f35,0x3f800000,0xbf35bf35,0x80003f80,0x3f35bf35,0xbf800000,0x3f353f35,0x8000bf80,0xbf353f35,0x3f800000,0xbf35bf35,
0x80003f80,0x3f35bf35,0xbf800000,0x3f353f35,0x8000bf80,0xbf353f35,0x3f800000,0xbf35bf35,0xbf800000,0x3f353f35,0xbf80,0xbf353f35,
0x3f800000,0xbf35bf35,0x3f80,0x3f35bf35,0xbf800000,0x3f353f35,0xbf80,0xbf353f35,0x3f800000,0xbf35bf35,0x3f80,0x3f35bf35,
0xbf800000,0x3f353f35,0xbf80,0xbf353f35,0x3f800000,0xbf35bf35,0x3f80,0x3f35bf35,0xbf800000,0x3f353f35,0xbf80,0xbf353f35,
0x3f800000,0xbf35bf35,0x3f80,0x3f35bf35,0x3f800000,0xbf55bf0e,0x3ec43f6d,0x3e48bf7b,0xbf353f35,0x3f7bbe48,0xbf6dbec4,0x3f0e3f55,
0x80003f80,0x3f0ebf55,0xbf6d3ec4,0x3f7b3e48,0xbf35bf35,0x3e483f7b,0x3ec4bf6d,0xbf553f0e,0xbf800000,0x3f553f0e,0xbec4bf6d,0xbe483f7b,
0x3f35bf35,0xbf7b3e48,0x3f6d3ec4,0xbf0ebf55,0x8000bf80,0xbf0e3f55,0x3f6dbec4,0xbf7bbe48,0x3f353f35,0xbe48bf7b,0xbec43f6d,0x3f55bf0e,
0x3f353f35,0xbe48bf7b,0xbec43f6d,0x3f55bf0e,0xbf80,0xbf0e3f55,0x3f6dbec4,0xbf7bbe48,0xbf353f35,0x3f7bbe48,0xbf6dbec4,0x3f0e3f55,
0x3f800000,0xbf55bf0e,0x3ec43f6d,0x3e48bf7b,0xbf35bf35,0x3e483f7b,0x3ec4bf6d,0xbf553f0e,0x3f80,0x3f0ebf55,0xbf6d3ec4,0x3f7b3e48,
0x3f35bf35,0xbf7b3e48,0x3f6d3ec4,0xbf0ebf55,0xbf800000,0x3f553f0e,0xbec4bf6d,0xbe483f7b,0x80003f80,0x3ec4bf6d,0xbf353f35,0x3f6dbec4,
0xbf800000,0x3f6d3ec4,0xbf35bf35,0x3ec43f6d,0x8000bf80,0xbec43f6d,0x3f35bf35,0xbf6d3ec4,0x3f800000,0xbf6dbec4,0x3f353f35,0xbec4bf6d,
0x80003f80,0x3ec4bf6d,0xbf353f35,0x3f6dbec4,0xbf800000,0x3f6d3ec4,0xbf35bf35,0x3ec43f6d,0x8000bf80,0xbec43f6d,0x3f35bf35,0xbf6d3ec4,
0x3f800000,0xbf6dbec4,0x3f353f35,0xbec4bf6d,0x3f80,0x3ec4bf6d,0xbf353f35,0x3f6dbec4,0x3f800000,0xbf6dbec4,0x3f353f35,0xbec4bf6d,
0xbf80,0xbec43f6d,0x3f35bf35,0xbf6d3ec4,0xbf800000,0x3f6d3ec4,0xbf35bf35,0x3ec43f6d,0x3f80,0x3ec4bf6d,0xbf353f35,0x3f6dbec4,
0x3f800000,0xbf6dbec4,0x3f353f35,0xbec4bf6d,0xbf80,0xbec43f6d,0x3f35bf35,0xbf6d3ec4,0xbf800000,0x3f6d3ec4,0xbf35bf35,0x3ec43f6d,
0x3f800000,0xbf7bbe48,0x3f6d3ec4,0xbf55bf0e,0x3f353f35,0xbf0ebf55,0x3ec43f6d,0xbe48bf7b,0x8000bf80,0xbe483f7b,0x3ec4bf6d,0xbf0e3f55,
0x3f35bf35,0xbf553f0e,0x3f6dbec4,0xbf7b3e48,0xbf800000,0x3f7b3e48,0xbf6dbec4,0x3f553f0e,0xbf35bf35,0x3f0e3f55,0xbec4bf6d,0x3e483f7b,
0x80003f80,0x3e48bf7b,0xbec43f6d,0x3f0ebf55,0xbf353f35,0x3f55bf0e,0xbf6d3ec4,0x3f7bbe48,0x3f35bf35,0xbf553f0e,0x3f6dbec4,0xbf7b3e48,
0xbf80,0xbe483f7b,0x3ec4bf6d,0xbf0e3f55,0xbf35bf35,0x3f0e3f55,0xbec4bf6d,0x3e483f7b,0xbf800000,0x3f7b3e48,0xbf6dbec4,0x3f553f0e,
0xbf353f35,0x3f55bf0e,0xbf6d3ec4,0x3f7bbe48,0x3f80,0x3e48bf7b,0xbec43f6d,0x3f0ebf55,0x3f353f35,0xbf0ebf55,0x3ec43f6d,0xbe48bf7b,
0x3f800000,0xbf7bbe48,0x3f6d3ec4,0xbf55bf0e,0x80003f80,0x8000bf80,0x80003f80,0x8000bf80,0x80003f80,0x8000bf80,0x80003f80,0x8000bf80,
0x80003f80,0x8000bf80,0x80003f80,0x8000bf80,0x80003f80,0x8000bf80,0x80003f80,0x8000bf80,0x80003f80,0x8000bf80,0x80003f80,0x8000bf80,
0x80003f80,0x8000bf80,0x80003f80,0x8000bf80,0x80003f80,0x8000bf80,0x80003f80,0x8000bf80,0x80003f80,0x8000bf80,0x80003f80,0x8000bf80,
0x3f800000,0xbf800000,0x3f800000,0xbf800000,0x3f800000,0xbf800000,0x3f800000,0xbf800000,0x3f800000,0xbf800000,0x3f800000,0xbf800000,
0x3f800000,0xbf800000,0x3f800000,0xbf800000,0x3f800000,0xbf800000,0x3f800000,0xbf800000,0x3f800000,0xbf800000,0x3f800000,0xbf800000,
0x3f800000,0xbf800000,0x3f800000,0xbf800000,0x3f800000,0xbf800000,0x3f800000,0xbf800000,0x3f800000,0xbf7b3e48,0x3f6dbec4,0xbf553f0e,
0x3f35bf35,0xbf0e3f55,0x3ec4bf6d,0xbe483f7b,0x80003f80,0xbe48bf7b,0x3ec43f6d,0xbf0ebf55,0x3f353f35,0xbf55bf0e,0x3f6d3ec4,0xbf7bbe48,
0xbf800000,0x3f7bbe48,0xbf6d3ec4,0x3f55bf0e,0xbf353f35,0x3f0ebf55,0xbec43f6d,0x3e48bf7b,0x8000bf80,0x3e483f7b,0xbec4bf6d,0x3f0e3f55,
0xbf35bf35,0x3f553f0e,0xbf6dbec4,0x3f7b3e48,0xbf35bf35,0x3f553f0e,0xbf6dbec4,0x3f7b3e48,0xbf80,0x3e483f7b,0xbec4bf6d,0x3f0e3f55,
0x3f35bf35,0xbf0e3f55,0x3ec4bf6d,0xbe483f7b,0x3f800000,0xbf7b3e48,0x3f6dbec4,0xbf553f0e,0x3f353f35,0xbf55bf0e,0x3f6d3ec4,0xbf7bbe48,
0x3f80,0xbe48bf7b,0x3ec43f6d,0xbf0ebf55,0xbf353f35,0x3f0ebf55,0xbec43f6d,0x3e48bf7b,0xbf800000,0x3f7bbe48,0xbf6d3ec4,0x3f55bf0e,
0x80003f80,0xbec4bf6d,0x3f353f35,0xbf6dbec4,0x3f800000,0xbf6d3ec4,0x3f35bf35,0xbec43f6d,0x8000bf80,0x3ec43f6d,0xbf35bf35,0x3f6d3ec4,
0xbf800000,0x3f6dbec4,0xbf353f35,0x3ec4bf6d,0x80003f80,0xbec4bf6d,0x3f353f35,0xbf6dbec4,0x3f800000,0xbf6d3ec4,0x3f35bf35,0xbec43f6d,
0x8000bf80,0x3ec43f6d,0xbf35bf35,0x3f6d3ec4,0xbf800000,0x3f6dbec4,0xbf353f35,0x3ec4bf6d,0xbf80,0x3ec43f6d,0xbf35bf35,0x3f6d3ec4,
0x3f800000,0xbf6d3ec4,0x3f35bf35,0xbec43f6d,0x3f80,0xbec4bf6d,0x3f353f35,0xbf6dbec4,0xbf800000,0x3f6dbec4,0xbf353f35,0x3ec4bf6d,
0xbf80,0x3ec43f6d,0xbf35bf35,0x3f6d3ec4,0x3f800000,0xbf6d3ec4,0x3f35bf35,0xbec43f6d,0x3f80,0xbec4bf6d,0x3f353f35,0xbf6dbec4,
0xbf800000,0x3f6dbec4,0xbf353f35,0x3ec4bf6d,0x3f800000,0xbf553f0e,0x3ec4bf6d,0x3e483f7b,0xbf35bf35,0x3f7b3e48,0xbf6d3ec4,0x3f0ebf55,
0x8000bf80,0x3f0e3f55,0xbf6dbec4,0x3f7bbe48,0xbf353f35,0x3e48bf7b,0x3ec43f6d,0xbf55bf0e,0xbf800000,0x3f55bf0e,0xbec43f6d,0xbe48bf7b,
0x3f353f35,0xbf7bbe48,0x3f6dbec4,0xbf0e3f55,0x80003f80,0xbf0ebf55,0x3f6d3ec4,0xbf7b3e48,0x3f35bf35,0xbe483f7b,0xbec4bf6d,0x3f553f0e,
0xbf353f35,0x3e48bf7b,0x3ec43f6d,0xbf55bf0e,0xbf80,0x3f0e3f55,0xbf6dbec4,0x3f7bbe48,0x3f353f35,0xbf7bbe48,0x3f6dbec4,0xbf0e3f55,
0xbf800000,0x3f55bf0e,0xbec43f6d,0xbe48bf7b,0x3f35bf35,0xbe483f7b,0xbec4bf6d,0x3f553f0e,0x3f80,0xbf0ebf55,0x3f6d3ec4,0xbf7b3e48,
0xbf35bf35,0x3f7b3e48,0xbf6d3ec4,0x3f0ebf55,0x3f800000,0xbf553f0e,0x3ec4bf6d,0x3e483f7b,0x80003f80,0xbf35bf35,0x3f800000,0xbf353f35,
0x8000bf80,0x3f353f35,0xbf800000,0x3f35bf35,0x80003f80,0xbf35bf35,0x3f800000,0xbf353f35,0x8000bf80,0x3f353f35,0xbf800000,0x3f35bf35,
0x80003f80,0xbf35bf35,0x3f800000,0xbf353f35,0x8000bf80,0x3f353f35,0xbf800000,0x3f35bf35,0x80003f80,0xbf35bf35,0x3f800000,0xbf353f35,
0x8000bf80,0x3f353f35,0xbf800000,0x3f35bf35,0xbf800000,0x3f35bf35,0x3f80,0xbf35bf35,0x3f800000,0xbf353f35,0xbf80,0x3f353f35,
0xbf800000,0x3f35bf35,0x3f80,0xbf35bf35,0x3f800000,0xbf353f35,0xbf80,0x3f353f35,0xbf800000,0x3f35bf35,0x3f80,0xbf35bf35,
0x3f800000,0xbf353f35,0xbf80,0x3f353f35,0xbf800000,0x3f35bf35,0x3f80,0xbf35bf35,0x3f800000,0xbf353f35,0xbf80,0x3f353f35,
0x3f800000,0xbf0e3f55,0xbec4bf6d,0x3f7b3e48,0xbf353f35,0xbe48bf7b,0x3f6d3ec4,0xbf553f0e,0x80003f80,0xbf55bf0e,0x3f6dbec4,0xbe483f7b,
0xbf35bf35,0x3f7bbe48,0xbec43f6d,0xbf0ebf55,0xbf800000,0x3f0ebf55,0x3ec43f6d,0xbf7bbe48,0x3f35bf35,0x3e483f7b,0xbf6dbec4,0x3f55bf0e,
0x8000bf80,0x3f553f0e,0xbf6d3ec4,0x3e48bf7b,0x3f353f35,0xbf7b3e48,0x3ec4bf6d,0x3f0e3f55,0x3f353f35,0xbf7b3e48,0x3ec4bf6d,0x3f0e3f55,
0xbf80,0x3f553f0e,0xbf6d3ec4,0x3e48bf7b,0xbf353f35,0xbe48bf7b,0x3f6d3ec4,0xbf553f0e,0x3f800000,0xbf0e3f55,0xbec4bf6d,0x3f7b3e48,
0xbf35bf35,0x3f7bbe48,0xbec43f6d,0xbf0ebf55,0x3f80,0xbf55bf0e,0x3f6dbec4,0xbe483f7b,0x3f35bf35,0x3e483f7b,0xbf6dbec4,0x3f55bf0e,
0xbf800000,0x3f0ebf55,0x3ec43f6d,0xbf7bbe48,0x80003f80,0xbf6dbec4,0x3f35bf35,0x3ec43f6d,0xbf800000,0x3ec4bf6d,0x3f353f35,0xbf6d3ec4,
0x8000bf80,0x3f6d3ec4,0xbf353f35,0xbec4bf6d,0x3f800000,0xbec43f6d,0xbf35bf35,0x3f6dbec4,0x80003f80,0xbf6dbec4,0x3f35bf35,0x3ec43f6d,
0xbf800000,0x3ec4bf6d,0x3f353f35,0xbf6d3ec4,0x8000bf80,0x3f6d3ec4,0xbf353f35,0xbec4bf6d,0x3f800000,0xbec43f6d,0xbf35bf35,0x3f6dbec4,
0x3f80,0xbf6dbec4,0x3f35bf35,0x3ec43f6d,0x3f800000,0xbec43f6d,0xbf35bf35,0x3f6dbec4,0xbf80,0x3f6d3ec4,0xbf353f35,0xbec4bf6d,
0xbf800000,0x3ec4bf6d,0x3f353f35,0xbf6d3ec4,0x3f80,0xbf6dbec4,0x3f35bf35,0x3ec43f6d,0x3f800000,0xbec43f6d,0xbf35bf35,0x3f6dbec4,
0xbf80,0x3f6d3ec4,0xbf353f35,0xbec4bf6d,0xbf800000,0x3ec4bf6d,0x3f353f35,0xbf6d3ec4,0x3f800000,0xbe483f7b,0xbf6dbec4,0x3f0ebf55,
0x3f353f35,0xbf553f0e,0xbec4bf6d,0x3f7bbe48,0x8000bf80,0x3f7b3e48,0xbec43f6d,0xbf55bf0e,0x3f35bf35,0x3f0e3f55,0xbf6d3ec4,0xbe48bf7b,
0xbf800000,0x3e48bf7b,0x3f6d3ec4,0xbf0e3f55,0xbf35bf35,0x3f55bf0e,0x3ec43f6d,0xbf7b3e48,0x80003f80,0xbf7bbe48,0x3ec4bf6d,0x3f553f0e,
0xbf353f35,0xbf0ebf55,0x3f6dbec4,0x3e483f7b,0x3f35bf35,0x3f0e3f55,0xbf6d3ec4,0xbe48bf7b,0xbf80,0x3f7b3e48,0xbec43f6d,0xbf55bf0e,
0xbf35bf35,0x3f55bf0e,0x3ec43f6d,0xbf7b3e48,0xbf800000,0x3e48bf7b,0x3f6d3ec4,0xbf0e3f55,0xbf353f35,0xbf0ebf55,0x3f6dbec4,0x3e483f7b,
0x3f80,0xbf7bbe48,0x3ec4bf6d,0x3f553f0e,0x3f353f35,0xbf553f0e,0xbec4bf6d,0x3f7bbe48,0x3f800000,0xbe483f7b,0xbf6dbec4,0x3f0ebf55,
0x80003f80,0xbf800000,0x8000bf80,0x3f800000,0x80003f80,0xbf800000,0x8000bf80,0x3f800000,0x80003f80,0xbf800000,0x8000bf80,0x3f800000,
0x80003f80,0xbf800000,0x8000bf80,0x3f800000,0x80003f80,0xbf800000,0x8000bf80,0x3f800000,0x80003f80,0xbf800000,0x8000bf80,0x3f800000,
0x80003f80,0xbf800000,0x8000bf80,0x3f800000,0x80003f80,0xbf800000,0x8000bf80,0x3f800000,0x3f800000,0x3f80,0xbf800000,0xbf80,
0x3f800000,0x3f80,0xbf800000,0xbf80,0x3f800000,0x3f80,0xbf800000,0xbf80,0x3f800000,0x3f80,0xbf800000,0xbf80,
0x3f800000,0x3f80,0xbf800000,0xbf80,0x3f800000,0x3f80,0xbf800000,0xbf80,0x3f800000,0x3f80,0xbf800000,0xbf80,
0x3f800000,0x3f80,0xbf800000,0xbf80,0x3f800000,0x3e483f7b,0xbf6d3ec4,0xbf0ebf55,0x3f35bf35,0x3f553f0e,0xbec43f6d,0xbf7bbe48,
0x80003f80,0xbf7b3e48,0xbec4bf6d,0x3f55bf0e,0x3f353f35,0xbf0e3f55,0xbf6dbec4,0x3e48bf7b,0xbf800000,0xbe48bf7b,0x3f6dbec4,0x3f0e3f55,
0xbf353f35,0xbf55bf0e,0x3ec4bf6d,0x3f7b3e48,0x8000bf80,0x3f7bbe48,0x3ec43f6d,0xbf553f0e,0xbf35bf35,0x3f0ebf55,0x3f6d3ec4,0xbe483f7b,
0xbf35bf35,0x3f0ebf55,0x3f6d3ec4,0xbe483f7b,0xbf80,0x3f7bbe48,0x3ec43f6d,0xbf553f0e,0x3f35bf35,0x3f553f0e,0xbec43f6d,0xbf7bbe48,
0x3f800000,0x3e483f7b,0xbf6d3ec4,0xbf0ebf55,0x3f353f35,0xbf0e3f55,0xbf6dbec4,0x3e48bf7b,0x3f80,0xbf7b3e48,0xbec4bf6d,0x3f55bf0e,
0xbf353f35,0xbf55bf0e,0x3ec4bf6d,0x3f7b3e48,0xbf800000,0xbe48bf7b,0x3f6dbec4,0x3f0e3f55,0x80003f80,0xbf6d3ec4,0xbf35bf35,0x3ec4bf6d,
0x3f800000,0x3ec43f6d,0xbf353f35,0xbf6dbec4,0x8000bf80,0x3f6dbec4,0x3f353f35,0xbec43f6d,0xbf800000,0xbec4bf6d,0x3f35bf35,0x3f6d3ec4,
0x80003f80,0xbf6d3ec4,0xbf35bf35,0x3ec4bf6d,0x3f800000,0x3ec43f6d,0xbf353f35,0xbf6dbec4,0x8000bf80,0x3f6dbec4,0x3f353f35,0xbec43f6d,
0xbf800000,0xbec4bf6d,0x3f35bf35,0x3f6d3ec4,0xbf80,0x3f6dbec4,0x3f353f35,0xbec43f6d,0x3f800000,0x3ec43f6d,0xbf353f35,0xbf6dbec4,
0x3f80,0xbf6d3ec4,0xbf35bf35,0x3ec4bf6d,0xbf800000,0xbec4bf6d,0x3f35bf35,0x3f6d3ec4,0xbf80,0x3f6dbec4,0x3f353f35,0xbec43f6d,
0x3f800000,0x3ec43f6d,0xbf353f35,0xbf6dbec4,0x3f80,0xbf6d3ec4,0xbf35bf35,0x3ec4bf6d,0xbf800000,0xbec4bf6d,0x3f35bf35,0x3f6d3ec4,
0x3f800000,0x3f0e3f55,0xbec43f6d,0xbf7b3e48,0xbf35bf35,0x3e48bf7b,0x3f6dbec4,0x3f553f0e,0x8000bf80,0x3f55bf0e,0x3f6d3ec4,0x3e483f7b,
0xbf353f35,0xbf7bbe48,0xbec4bf6d,0x3f0ebf55,0xbf800000,0xbf0ebf55,0x3ec4bf6d,0x3f7bbe48,0x3f353f35,0xbe483f7b,0xbf6d3ec4,0xbf55bf0e,
0x80003f80,0xbf553f0e,0xbf6dbec4,0xbe48bf7b,0x3f35bf35,0x3f7b3e48,0x3ec43f6d,0xbf0e3f55,0xbf353f35,0xbf7bbe48,0xbec4bf6d,0x3f0ebf55,
0xbf80,0x3f55bf0e,0x3f6d3ec4,0x3e483f7b,0x3f353f35,0xbe483f7b,0xbf6d3ec4,0xbf55bf0e,0xbf800000,0xbf0ebf55,0x3ec4bf6d,0x3f7bbe48,
0x3f35bf35,0x3f7b3e48,0x3ec43f6d,0xbf0e3f55,0x3f80,0xbf553f0e,0xbf6dbec4,0xbe48bf7b,0xbf35bf35,0x3e48bf7b,0x3f6dbec4,0x3f553f0e,
0x3f800000,0x3f0e3f55,0xbec43f6d,0xbf7b3e48,0x80003f80,0xbf353f35,0xbf800000,0xbf35bf35,0x8000bf80,0x3f35bf35,0x3f800000,0x3f353f35,
0x80003f80,0xbf353f35,0xbf800000,0xbf35bf35,0x8000bf80,0x3f35bf35,0x3f800000,0x3f353f35,0x80003f80,0xbf353f35,0xbf800000,0xbf35bf35,
0x8000bf80,0x3f35bf35,0x3f800000,0x3f353f35,0x80003f80,0xbf353f35,0xbf800000,0xbf35bf35,0x8000bf80,0x3f35bf35,0x3f800000,0x3f353f35,
0xbf800000,0xbf35bf35,0xbf80,0x3f35bf35,0x3f800000,0x3f353f35,0x3f80,0xbf353f35,0xbf800000,0xbf35bf35,0xbf80,0x3f35bf35,
0x3f800000,0x3f353f35,0x3f80,0xbf353f35,0xbf800000,0xbf35bf35,0xbf80,0x3f35bf35,0x3f800000,0x3f353f35,0x3f80,0xbf353f35,
0xbf800000,0xbf35bf35,0xbf80,0x3f35bf35,0x3f800000,0x3f353f35,0x3f80,0xbf353f35,0x3f800000,0x3f553f0e,0x3ec43f6d,0xbe483f7b,
0xbf353f35,0xbf7b3e48,0xbf6dbec4,0xbf0ebf55,0x80003f80,0xbf0e3f55,0xbf6d3ec4,0xbf7bbe48,0xbf35bf35,0xbe48bf7b,0x3ec4bf6d,0x3f55bf0e,
0xbf800000,0xbf55bf0e,0xbec4bf6d,0x3e48bf7b,0x3f35bf35,0x3f7bbe48,0x3f6d3ec4,0x3f0e3f55,0x8000bf80,0x3f0ebf55,0x3f6dbec4,0x3f7b3e48,
0x3f353f35,0x3e483f7b,0xbec43f6d,0xbf553f0e,0x3f353f35,0x3e483f7b,0xbec43f6d,0xbf553f0e,0xbf80,0x3f0ebf55,0x3f6dbec4,0x3f7b3e48,
0xbf353f35,0xbf7b3e48,0xbf6dbec4,0xbf0ebf55,0x3f800000,0x3f553f0e,0x3ec43f6d,0xbe483f7b,0xbf35bf35,0xbe48bf7b,0x3ec4bf6d,0x3f55bf0e,
0x3f80,0xbf0e3f55,0xbf6d3ec4,0xbf7bbe48,0x3f35bf35,0x3f7bbe48,0x3f6d3ec4,0x3f0e3f55,0xbf800000,0xbf55bf0e,0xbec4bf6d,0x3e48bf7b,
0x80003f80,0xbec43f6d,0xbf353f35,0xbf6d3ec4,0xbf800000,0xbf6dbec4,0xbf35bf35,0xbec4bf6d,0x8000bf80,0x3ec4bf6d,0x3f35bf35,0x3f6dbec4,
0x3f800000,0x3f6d3ec4,0x3f353f35,0x3ec43f6d,0x80003f80,0xbec43f6d,0xbf353f35,0xbf6d3ec4,0xbf800000,0xbf6dbec4,0xbf35bf35,0xbec4bf6d,
0x8000bf80,0x3ec4bf6d,0x3f35bf35,0x3f6dbec4,0x3f800000,0x3f6d3ec4,0x3f353f35,0x3ec43f6d,0x3f80,0xbec43f6d,0xbf353f35,0xbf6d3ec4,
0x3f800000,0x3f6d3ec4,0x3f353f35,0x3ec43f6d,0xbf80,0x3ec4bf6d,0x3f35bf35,0x3f6dbec4,0xbf800000,0xbf6dbec4,0xbf35bf35,0xbec4bf6d,
0x3f80,0xbec43f6d,0xbf353f35,0xbf6d3ec4,0x3f800000,0x3f6d3ec4,0x3f353f35,0x3ec43f6d,0xbf80,0x3ec4bf6d,0x3f35bf35,0x3f6dbec4,
0xbf800000,0xbf6dbec4,0xbf35bf35,0xbec4bf6d,0x3f800000,0x3f7b3e48,0x3f6d3ec4,0x3f553f0e,0x3f353f35,0x3f0e3f55,0x3ec43f6d,0x3e483f7b,
0x8000bf80,0x3e48bf7b,0x3ec4bf6d,0x3f0ebf55,0x3f35bf35,0x3f55bf0e,0x3f6dbec4,0x3f7bbe48,0xbf800000,0xbf7bbe48,0xbf6dbec4,0xbf55bf0e,
0xbf35bf35,0xbf0ebf55,0xbec4bf6d,0xbe48bf7b,0x80003f80,0xbe483f7b,0xbec43f6d,0xbf0e3f55,0xbf353f35,0xbf553f0e,0xbf6d3ec4,0xbf7b3e48,
0x3f35bf35,0x3f55bf0e,0x3f6dbec4,0x3f7bbe48,0xbf80,0x3e48bf7b,0x3ec4bf6d,0x3f0ebf55,0xbf35bf35,0xbf0ebf55,0xbec4bf6d,0xbe48bf7b,
0xbf800000,0xbf7bbe48,0xbf6dbec4,0xbf55bf0e,0xbf353f35,0xbf553f0e,0xbf6d3ec4,0xbf7b3e48,0x3f80,0xbe483f7b,0xbec43f6d,0xbf0e3f55,
0x3f353f35,0x3f0e3f55,0x3ec43f6d,0x3e483f7b,0x3f800000,0x3f7b3e48,0x3f6d3ec4,0x3f553f0e,0x80003f80,0x80003f80,0x80003f80,0x80003f80,
0x80003f80,0x80003f80,0x80003f80,0x80003f80,0x80003f80,0x80003f80,0x80003f80,0x80003f80,0x80003f80,0x80003f80,0x80003f80,0x80003f80,
0x80003f80,0x80003f80,0x80003f80,0x80003f80,0x80003f80,0x80003f80,0x80003f80,0x80003f80,0x80003f80,0x80003f80,0x80003f80,0x80003f80,
0x80003f80,0x80003f80,0x80003f80,0x80003f80,0x3f800000,0x3f800000,0x3f800000,0x3f800000,0x3f800000,0x3f800000,0x3f800000,0x3f800000,
0x3f800000,0x3f800000,0x3f800000,0x3f800000,0x3f800000,0x3f800000,0x3f800000,0x3f800000,0x3f800000,0x3f800000,0x3f800000,0x3f800000,
0x3f800000,0x3f800000,0x3f800000,0x3f800000,0x3f800000,0x3f800000,0x3f800000,0x3f800000,0x3f800000,0x3f800000,0x3f800000,0x3f800000,
0x80003f80,0x3f353f35,0x3f800000,0x3f35bf35,0x8000bf80,0xbf35bf35,0xbf800000,0xbf353f35,0x80003f80,0x3f353f35,0x3f800000,0x3f35bf35,
0x8000bf80,0xbf35bf35,0xbf800000,0xbf353f35,0x80003f80,0x3f353f35,0x3f800000,0x3f35bf35,0x8000bf80,0xbf35bf35,0xbf800000,0xbf353f35,
0x80003f80,0x3f353f35,0x3f800000,0x3f35bf35,0x8000bf80,0xbf35bf35,0xbf800000,0xbf353f35,0xbf800000,0xbf353f35,0x3f80,0x3f353f35,
0x3f800000,0x3f35bf35,0xbf80,0xbf35bf35,0xbf800000,0xbf353f35,0x3f80,0x3f353f35,0x3f800000,0x3f35bf35,0xbf80,0xbf35bf35,
0xbf800000,0xbf353f35,0x3f80,0x3f353f35,0x3f800000,0x3f35bf35,0xbf80,0xbf35bf35,0xbf800000,0xbf353f35,0x3f80,0x3f353f35,
0x3f800000,0x3f35bf35,0xbf80,0xbf35bf35,0x80003f80,0x3f800000,0x8000bf80,0xbf800000,0x80003f80,0x3f800000,0x8000bf80,0xbf800000,
0x80003f80,0x3f800000,0x8000bf80,0xbf800000,0x80003f80,0x3f800000,0x8000bf80,0xbf800000,0x80003f80,0x3f800000,0x8000bf80,0xbf800000,
0x80003f80,0x3f800000,0x8000bf80,0xbf800000,0x80003f80,0x3f800000,0x8000bf80,0xbf800000,0x80003f80,0x3f800000,0x8000bf80,0xbf800000,
0x3f800000,0xbf80,0xbf800000,0x3f80,0x3f800000,0xbf80,0xbf800000,0x3f80,0x3f800000,0xbf80,0xbf800000,0x3f80,
0x3f800000,0xbf80,0xbf800000,0x3f80,0x3f800000,0xbf80,0xbf800000,0x3f80,0x3f800000,0xbf80,0xbf800000,0x3f80,
0x3f800000,0xbf80,0xbf800000,0x3f80,0x3f800000,0xbf80,0xbf800000,0x3f80,0x80003f80,0x3f35bf35,0xbf800000,0x3f353f35,
0x8000bf80,0xbf353f35,0x3f800000,0xbf35bf35,0x80003f80,0x3f35bf35,0xbf800000,0x3f353f35,0x8000bf80,0xbf353f35,0x3f800000,0xbf35bf35,
0x80003f80,0x3f35bf35,0xbf800000,0x3f353f35,0x8000bf80,0xbf353f35,0x3f800000,0xbf35bf35,0x80003f80,0x3f35bf35,0xbf800000,0x3f353f35,
0x8000bf80,0xbf353f35,0x3f800000,0xbf35bf35,0xbf800000,0x3f353f35,0xbf80,0xbf353f35,0x3f800000,0xbf35bf35,0x3f80,0x3f35bf35,
0xbf800000,0x3f353f35,0xbf80,0xbf353f35,0x3f800000,0xbf35bf35,0x3f80,0x3f35bf35,0xbf800000,0x3f353f35,0xbf80,0xbf353f35,
0x3f800000,0xbf35bf35,0x3f80,0x3f35bf35,0xbf800000,0x3f353f35,0xbf80,0xbf353f35,0x3f800000,0xbf35bf35,0x3f80,0x3f35bf35,
0x80003f80,0x3e483f7b,0x3ec43f6d,0x3f0e3f55,0x3f353f35,0x3f553f0e,0x3f6d3ec4,0x3f7b3e48,0x3f800000,0x3f7bbe48,0x3f6dbec4,0x3f55bf0e,
0x3f35bf35,0x3f0ebf55,0x3ec4bf6d,0x3e48bf7b,0x8000bf80,0xbe48bf7b,0xbec4bf6d,0xbf0ebf55,0xbf35bf35,0xbf55bf0e,0xbf6dbec4,0xbf7bbe48,
0xbf800000,0xbf7b3e48,0xbf6d3ec4,0xbf553f0e,0xbf353f35,0xbf0e3f55,0xbec43f6d,0xbe483f7b,0x3f35bf35,0x3f0ebf55,0x3ec4bf6d,0x3e48bf7b,
0x3f800000,0x3f7bbe48,0x3f6dbec4,0x3f55bf0e,0xbf35bf35,0xbf55bf0e,0xbf6dbec4,0xbf7bbe48,0xbf80,0xbe48bf7b,0xbec4bf6d,0xbf0ebf55,
0xbf353f35,0xbf0e3f55,0xbec43f6d,0xbe483f7b,0xbf800000,0xbf7b3e48,0xbf6d3ec4,0xbf553f0e,0x3f353f35,0x3f553f0e,0x3f6d3ec4,0x3f7b3e48,
0x3f80,0x3e483f7b,0x3ec43f6d,0x3f0e3f55,0x3f800000,0x3f0ebf55,0xbec4bf6d,0xbf7bbe48,0xbf353f35,0x3e483f7b,0x3f6d3ec4,0x3f55bf0e,
0x80003f80,0x3f553f0e,0x3f6dbec4,0x3e48bf7b,0xbf35bf35,0xbf7b3e48,0xbec43f6d,0x3f0e3f55,0xbf800000,0xbf0e3f55,0x3ec43f6d,0x3f7b3e48,
0x3f35bf35,0xbe48bf7b,0xbf6dbec4,0xbf553f0e,0x8000bf80,0xbf55bf0e,0xbf6d3ec4,0xbe483f7b,0x3f353f35,0x3f7bbe48,0x3ec4bf6d,0xbf0ebf55,
0x3f353f35,0x3f7bbe48,0x3ec4bf6d,0xbf0ebf55,0xbf80,0xbf55bf0e,0xbf6d3ec4,0xbe483f7b,0xbf353f35,0x3e483f7b,0x3f6d3ec4,0x3f55bf0e,
0x3f800000,0x3f0ebf55,0xbec4bf6d,0xbf7bbe48,0xbf35bf35,0xbf7b3e48,0xbec43f6d,0x3f0e3f55,0x3f80,0x3f553f0e,0x3f6dbec4,0x3e48bf7b,
0x3f35bf35,0xbe48bf7b,0xbf6dbec4,0xbf553f0e,0xbf800000,0xbf0e3f55,0x3ec43f6d,0x3f7b3e48,0x8000bf80,0xbf7b3e48,0x3ec43f6d,0x3f55bf0e,
0xbf35bf35,0xbf0e3f55,0x3f6d3ec4,0x3e48bf7b,0xbf800000,0x3e483f7b,0x3f6dbec4,0xbf0ebf55,0xbf353f35,0x3f553f0e,0x3ec4bf6d,0xbf7bbe48,
0x80003f80,0x3f7bbe48,0xbec4bf6d,0xbf553f0e,0x3f353f35,0x3f0ebf55,0xbf6dbec4,0xbe483f7b,0x3f800000,0xbe48bf7b,0xbf6d3ec4,0x3f0e3f55,
0x3f35bf35,0xbf55bf0e,0xbec43f6d,0x3f7b3e48,0xbf353f35,0x3f553f0e,0x3ec4bf6d,0xbf7bbe48,0xbf800000,0x3e483f7b,0x3f6dbec4,0xbf0ebf55,
0x3f353f35,0x3f0ebf55,0xbf6dbec4,0xbe483f7b,0x3f80,0x3f7bbe48,0xbec4bf6d,0xbf553f0e,0x3f35bf35,0xbf55bf0e,0xbec43f6d,0x3f7b3e48,
0x3f800000,0xbe48bf7b,0xbf6d3ec4,0x3f0e3f55,0xbf35bf35,0xbf0e3f55,0x3f6d3ec4,0x3e48bf7b,0xbf80,0xbf7b3e48,0x3ec43f6d,0x3f55bf0e,
0xbf800000,0x3f553f0e,0xbec4bf6d,0xbe483f7b,0x3f35bf35,0xbf7b3e48,0x3f6d3ec4,0xbf0ebf55,0x8000bf80,0xbf0e3f55,0x3f6dbec4,0xbf7bbe48,
0x3f353f35,0xbe48bf7b,0xbec43f6d,0x3f55bf0e,0x3f800000,0xbf55bf0e,0x3ec43f6d,0x3e48bf7b,0xbf353f35,0x3f7bbe48,0xbf6dbec4,0x3f0e3f55,
0x80003f80,0x3f0ebf55,0xbf6d3ec4,0x3f7b3e48,0xbf35bf35,0x3e483f7b,0x3ec4bf6d,0xbf553f0e,0xbf35bf35,0x3e483f7b,0x3ec4bf6d,0xbf553f0e,
0x3f80,0x3f0ebf55,0xbf6d3ec4,0x3f7b3e48,0x3f35bf35,0xbf7b3e48,0x3f6d3ec4,0xbf0ebf55,0xbf800000,0x3f553f0e,0xbec4bf6d,0xbe483f7b,
0x3f353f35,0xbe48bf7b,0xbec43f6d,0x3f55bf0e,0xbf80,0xbf0e3f55,0x3f6dbec4,0xbf7bbe48,0xbf353f35,0x3f7bbe48,0xbf6dbec4,0x3f0e3f55,
0x3f800000,0xbf55bf0e,0x3ec43f6d,0x3e48bf7b,0x80003f80,0x3ec43f6d,0x3f353f35,0x3f6d3ec4,0x3f800000,0x3f6dbec4,0x3f35bf35,0x3ec4bf6d,
0x8000bf80,0xbec4bf6d,0xbf35bf35,0xbf6dbec4,0xbf800000,0xbf6d3ec4,0xbf353f35,0xbec43f6d,0x80003f80,0x3ec43f6d,0x3f353f35,0x3f6d3ec4,
0x3f800000,0x3f6dbec4,0x3f35bf35,0x3ec4bf6d,0x8000bf80,0xbec4bf6d,0xbf35bf35,0xbf6dbec4,0xbf800000,0xbf6d3ec4,0xbf353f35,0xbec43f6d,
0xbf80,0xbec4bf6d,0xbf35bf35,0xbf6dbec4,0x3f800000,0x3f6dbec4,0x3f35bf35,0x3ec4bf6d,0x3f80,0x3ec43f6d,0x3f353f35,0x3f6d3ec4,
0xbf800000,0xbf6d3ec4,0xbf353f35,0xbec43f6d,0xbf80,0xbec4bf6d,0xbf35bf35,0xbf6dbec4,0x3f800000,0x3f6dbec4,0x3f35bf35,0x3ec4bf6d,
0x3f80,0x3ec43f6d,0x3f353f35,0x3f6d3ec4,0xbf800000,0xbf6d3ec4,0xbf353f35,0xbec43f6d,0x8000bf80,0xbf6dbec4,0xbf353f35,0x3ec43f6d,
0x3f800000,0x3ec4bf6d,0xbf35bf35,0xbf6d3ec4,0x80003f80,0x3f6d3ec4,0x3f35bf35,0xbec4bf6d,0xbf800000,0xbec43f6d,0x3f353f35,0x3f6dbec4,
0x8000bf80,0xbf6dbec4,0xbf353f35,0x3ec43f6d,0x3f800000,0x3ec4bf6d,0xbf35bf35,0xbf6d3ec4,0x80003f80,0x3f6d3ec4,0x3f35bf35,0xbec4bf6d,
0xbf800000,0xbec43f6d,0x3f353f35,0x3f6dbec4,0xbf80,0xbf6dbec4,0xbf353f35,0x3ec43f6d,0xbf800000,0xbec43f6d,0x3f353f35,0x3f6dbec4,
0x3f80,0x3f6d3ec4,0x3f35bf35,0xbec4bf6d,0x3f800000,0x3ec4bf6d,0xbf35bf35,0xbf6d3ec4,0xbf80,0xbf6dbec4,0xbf353f35,0x3ec43f6d,
0xbf800000,0xbec43f6d,0x3f353f35,0x3f6dbec4,0x3f80,0x3f6d3ec4,0x3f35bf35,0xbec4bf6d,0x3f800000,0x3ec4bf6d,0xbf35bf35,0xbf6d3ec4,
0x80003f80,0x3f6dbec4,0xbf35bf35,0xbec43f6d,0x3f800000,0xbec4bf6d,0xbf353f35,0x3f6d3ec4,0x8000bf80,0xbf6d3ec4,0x3f353f35,0x3ec4bf6d,
0xbf800000,0x3ec43f6d,0x3f35bf35,0xbf6dbec4,0x80003f80,0x3f6dbec4,0xbf35bf35,0xbec43f6d,0x3f800000,0xbec4bf6d,0xbf353f35,0x3f6d3ec4,
0x8000bf80,0xbf6d3ec4,0x3f353f35,0x3ec4bf6d,0xbf800000,0x3ec43f6d,0x3f35bf35,0xbf6dbec4,0xbf80,0xbf6d3ec4,0x3f353f35,0x3ec4bf6d,
0x3f800000,0xbec4bf6d,0xbf353f35,0x3f6d3ec4,0x3f80,0x3f6dbec4,0xbf35bf35,0xbec43f6d,0xbf800000,0x3ec43f6d,0x3f35bf35,0xbf6dbec4,
0xbf80,0xbf6d3ec4,0x3f353f35,0x3ec4bf6d,0x3f800000,0xbec4bf6d,0xbf353f35,0x3f6d3ec4,0x3f80,0x3f6dbec4,0xbf35bf35,0xbec43f6d,
0xbf800000,0x3ec43f6d,0x3f35bf35,0xbf6dbec4,0x8000bf80,0xbec43f6d,0x3f35bf35,0xbf6d3ec4,0x3f800000,0xbf6dbec4,0x3f353f35,0xbec4bf6d,
0x80003f80,0x3ec4bf6d,0xbf353f35,0x3f6dbec4,0xbf800000,0x3f6d3ec4,0xbf35bf35,0x3ec43f6d,0x8000bf80,0xbec43f6d,0x3f35bf35,0xbf6d3ec4,
0x3f800000,0xbf6dbec4,0x3f353f35,0xbec4bf6d,0x80003f80,0x3ec4bf6d,0xbf353f35,0x3f6dbec4,0xbf800000,0x3f6d3ec4,0xbf35bf35,0x3ec43f6d,
0xbf80,0xbec43f6d,0x3f35bf35,0xbf6d3ec4,0xbf800000,0x3f6d3ec4,0xbf35bf35,0x3ec43f6d,0x3f80,0x3ec4bf6d,0xbf353f35,0x3f6dbec4,
0x3f800000,0xbf6dbec4,0x3f353f35,0xbec4bf6d,0xbf80,0xbec43f6d,0x3f35bf35,0xbf6d3ec4,0xbf800000,0x3f6d3ec4,0xbf35bf35,0x3ec43f6d,
0x3f80,0x3ec4bf6d,0xbf353f35,0x3f6dbec4,0x3f800000,0xbf6dbec4,0x3f353f35,0xbec4bf6d,0x80003f80,0x3f0e3f55,0x3f6d3ec4,0x3f7bbe48,
0x3f35bf35,0x3e48bf7b,0xbec4bf6d,0xbf55bf0e,0xbf800000,0xbf553f0e,0xbec43f6d,0x3e483f7b,0x3f353f35,0x3f7b3e48,0x3f6dbec4,0x3f0ebf55,
0x8000bf80,0xbf0ebf55,0xbf6dbec4,0xbf7b3e48,0xbf353f35,0xbe483f7b,0x3ec43f6d,0x3f553f0e,0x3f800000,0x3f55bf0e,0x3ec4bf6d,0xbe48bf7b,
0xbf35bf35,0xbf7bbe48,0xbf6d3ec4,0xbf0e3f55,0xbf35bf35,0xbf7bbe48,0xbf6d3ec4,0xbf0e3f55,0x3f800000,0x3f55bf0e,0x3ec4bf6d,0xbe48bf7b,
0x3f35bf35,0x3e48bf7b,0xbec4bf6d,0xbf55bf0e,0x3f80,0x3f0e3f55,0x3f6d3ec4,0x3f7bbe48,0x3f353f35,0x3f7b3e48,0x3f6dbec4,0x3f0ebf55,
0xbf800000,0xbf553f0e,0xbec43f6d,0x3e483f7b,0xbf353f35,0xbe483f7b,0x3ec43f6d,0x3f553f0e,0xbf80,0xbf0ebf55,0xbf6dbec4,0xbf7b3e48,
0xbf800000,0xbe483f7b,0x3f6d3ec4,0x3f0ebf55,0xbf35bf35,0xbf553f0e,0x3ec43f6d,0x3f7bbe48,0x80003f80,0x3f7b3e48,0x3ec4bf6d,0xbf55bf0e,
0xbf353f35,0x3f0e3f55,0x3f6dbec4,0xbe48bf7b,0x3f800000,0x3e48bf7b,0xbf6dbec4,0xbf0e3f55,0x3f353f35,0x3f55bf0e,0xbec4bf6d,0xbf7b3e48,
0x8000bf80,0xbf7bbe48,0xbec43f6d,0x3f553f0e,0x3f35bf35,0xbf0ebf55,0xbf6d3ec4,0x3e483f7b,0xbf353f35,0x3f0e3f55,0x3f6dbec4,0xbe48bf7b,
0x3f80,0x3f7b3e48,0x3ec4bf6d,0xbf55bf0e,0x3f353f35,0x3f55bf0e,0xbec4bf6d,0xbf7b3e48,0x3f800000,0x3e48bf7b,0xbf6dbec4,0xbf0e3f55,
0x3f35bf35,0xbf0ebf55,0xbf6d3ec4,0x3e483f7b,0xbf80,0xbf7bbe48,0xbec43f6d,0x3f553f0e,0xbf35bf35,0xbf553f0e,0x3ec43f6d,0x3f7bbe48,
0xbf800000,0xbe483f7b,0x3f6d3ec4,0x3f0ebf55,0x8000bf80,0xbf553f0e,0x3f6d3ec4,0xbe48bf7b,0xbf353f35,0x3f7b3e48,0xbec4bf6d,0xbf0e3f55,
0x3f800000,0xbf0ebf55,0xbec43f6d,0x3f7bbe48,0xbf35bf35,0xbe483f7b,0x3f6dbec4,0xbf55bf0e,0x80003f80,0x3f55bf0e,0xbf6dbec4,0x3e483f7b,
0x3f35bf35,0xbf7bbe48,0x3ec43f6d,0x3f0ebf55,0xbf800000,0x3f0e3f55,0x3ec4bf6d,0xbf7b3e48,0x3f353f35,0x3e48bf7b,0xbf6d3ec4,0x3f553f0e,
0x3f353f35,0x3e48bf7b,0xbf6d3ec4,0x3f553f0e,0xbf800000,0x3f0e3f55,0x3ec4bf6d,0xbf7b3e48,0xbf353f35,0x3f7b3e48,0xbec4bf6d,0xbf0e3f55,
0xbf80,0xbf553f0e,0x3f6d3ec4,0xbe48bf7b,0xbf35bf35,0xbe483f7b,0x3f6dbec4,0xbf55bf0e,0x3f800000,0xbf0ebf55,0xbec43f6d,0x3f7bbe48,
0x3f35bf35,0xbf7bbe48,0x3ec43f6d,0x3f0ebf55,0x3f80,0x3f55bf0e,0xbf6dbec4,0x3e483f7b,0x3f800000,0xbf7bbe48,0x3f6d3ec4,0xbf55bf0e,
0x3f353f35,0xbf0ebf55,0x3ec43f6d,0xbe48bf7b,0x8000bf80,0xbe483f7b,0x3ec4bf6d,0xbf0e3f55,0x3f35bf35,0xbf553f0e,0x3f6dbec4,0xbf7b3e48,
0xbf800000,0x3f7b3e48,0xbf6dbec4,0x3f553f0e,0xbf35bf35,0x3f0e3f55,0xbec4bf6d,0x3e483f7b,0x80003f80,0x3e48bf7b,0xbec43f6d,0x3f0ebf55,
0xbf353f35,0x3f55bf0e,0xbf6d3ec4,0x3f7bbe48,0x3f35bf35,0xbf553f0e,0x3f6dbec4,0xbf7b3e48,0xbf80,0xbe483f7b,0x3ec4bf6d,0xbf0e3f55,
0xbf35bf35,0x3f0e3f55,0xbec4bf6d,0x3e483f7b,0xbf800000,0x3f7b3e48,0xbf6dbec4,0x3f553f0e,0xbf353f35,0x3f55bf0e,0xbf6d3ec4,0x3f7bbe48,
0x3f80,0x3e48bf7b,0xbec43f6d,0x3f0ebf55,0x3f353f35,0xbf0ebf55,0x3ec43f6d,0xbe48bf7b,0x3f800000,0xbf7bbe48,0x3f6d3ec4,0xbf55bf0e,
0x80003f80,0x8000bf80,0x80003f80,0x8000bf80,0x80003f80,0x8000bf80,0x80003f80,0x8000bf80,0x80003f80,0x8000bf80,0x80003f80,0x8000bf80,
0x80003f80,0x8000bf80,0x80003f80,0x8000bf80,0x80003f80,0x8000bf80,0x80003f80,0x8000bf80,0x80003f80,0x8000bf80,0x80003f80,0x8000bf80,
0x80003f80,0x8000bf80,0x80003f80,0x8000bf80,0x80003f80,0x8000bf80,0x80003f80,0x8000bf80,0x3f800000,0xbf800000,0x3f800000,0xbf800000,
0x3f800000,0xbf800000,0x3f800000,0xbf800000,0x3f800000,0xbf800000,0x3f800000,0xbf800000,0x3f800000,0xbf800000,0x3f800000,0xbf800000,
0x3f800000,0xbf800000,0x3f800000,0xbf800000,0x3f800000,0xbf800000,0x3f800000,0xbf800000,0x3f800000,0xbf800000,0x3f800000,0xbf800000,
0x3f800000,0xbf800000,0x3f800000,0xbf800000,0x80003f80,0xbf35bf35,0x3f800000,0xbf353f35,0x8000bf80,0x3f353f35,0xbf800000,0x3f35bf35,
0x80003f80,0xbf35bf35,0x3f800000,0xbf353f35,0x8000bf80,0x3f353f35,0xbf800000,0x3f35bf35,0x80003f80,0xbf35bf35,0x3f800000,0xbf353f35,
0x8000bf80,0x3f353f35,0xbf800000,0x3f35bf35,0x80003f80,0xbf35bf35,0x3f800000,0xbf353f35,0x8000bf80,0x3f353f35,0xbf800000,0x3f35bf35,
0xbf800000,0x3f35bf35,0x3f80,0xbf35bf35,0x3f800000,0xbf353f35,0xbf80,0x3f353f35,0xbf800000,0x3f35bf35,0x3f80,0xbf35bf35,
0x3f800000,0xbf353f35,0xbf80,0x3f353f35,0xbf800000,0x3f35bf35,0x3f80,0xbf35bf35,0x3f800000,0xbf353f35,0xbf80,0x3f353f35,
0xbf800000,0x3f35bf35,0x3f80,0xbf35bf35,0x3f800000,0xbf353f35,0xbf80,0x3f353f35,0x80003f80,0xbf800000,0x8000bf80,0x3f800000,
0x80003f80,0xbf800000,0x8000bf80,0x3f800000,0x80003f80,0xbf800000,0x8000bf80,0x3f800000,0x80003f80,0xbf800000,0x8000bf80,0x3f800000,
0x80003f80,0xbf800000,0x8000bf80,0x3f800000,0x80003f80,0xbf800000,0x8000bf80,0x3f800000,0x80003f80,0xbf800000,0x8000bf80,0x3f800000,
0x80003f80,0xbf800000,0x8000bf80,0x3f800000,0x3f800000,0x3f80,0xbf800000,0xbf80,0x3f800000,0x3f80,0xbf800000,0xbf80,
0x3f800000,0x3f80,0xbf800000,0xbf80,0x3f800000,0x3f80,0xbf800000,0xbf80,0x3f800000,0x3f80,0xbf800000,0xbf80,
0x3f800000,0x3f80,0xbf800000,0xbf80,0x3f800000,0x3f80,0xbf800000,0xbf80,0x3f800000,0x3f80,0xbf800000,0xbf80,
0x80003f80,0xbf353f35,0xbf800000,0xbf35bf35,0x8000bf80,0x3f35bf35,0x3f800000,0x3f353f35,0x80003f80,0xbf353f35,0xbf800000,0xbf35bf35,
0x8000bf80,0x3f35bf35,0x3f800000,0x3f353f35,0x80003f80,0xbf353f35,0xbf800000,0xbf35bf35,0x8000bf80,0x3f35bf35,0x3f800000,0x3f353f35,
0x80003f80,0xbf353f35,0xbf800000,0xbf35bf35,0x8000bf80,0x3f35bf35,0x3f800000,0x3f353f35,0xbf800000,0xbf35bf35,0xbf80,0x3f35bf35,
0x3f800000,0x3f353f35,0x3f80,0xbf353f35,0xbf800000,0xbf35bf35,0xbf80,0x3f35bf35,0x3f800000,0x3f353f35,0x3f80,0xbf353f35,
0xbf800000,0xbf35bf35,0xbf80,0x3f35bf35,0x3f800000,0x3f353f35,0x3f80,0xbf353f35,0xbf800000,0xbf35bf35,0xbf80,0x3f35bf35,
0x3f800000,0x3f353f35,0x3f80,0xbf353f35,0x80003f80,0xbe48bf7b,0x3ec43f6d,0xbf0ebf55,0x3f353f35,0xbf55bf0e,0x3f6d3ec4,0xbf7bbe48,
0x3f800000,0xbf7b3e48,0x3f6dbec4,0xbf553f0e,0x3f35bf35,0xbf0e3f55,0x3ec4bf6d,0xbe483f7b,0x8000bf80,0x3e483f7b,0xbec4bf6d,0x3f0e3f55,
0xbf35bf35,0x3f553f0e,0xbf6dbec4,0x3f7b3e48,0xbf800000,0x3f7bbe48,0xbf6d3ec4,0x3f55bf0e,0xbf353f35,0x3f0ebf55,0xbec43f6d,0x3e48bf7b,
0x3f35bf35,0xbf0e3f55,0x3ec4bf6d,0xbe483f7b,0x3f800000,0xbf7b3e48,0x3f6dbec4,0xbf553f0e,0xbf35bf35,0x3f553f0e,0xbf6dbec4,0x3f7b3e48,
0xbf80,0x3e483f7b,0xbec4bf6d,0x3f0e3f55,0xbf353f35,0x3f0ebf55,0xbec43f6d,0x3e48bf7b,0xbf800000,0x3f7bbe48,0xbf6d3ec4,0x3f55bf0e,
0x3f353f35,0xbf55bf0e,0x3f6d3ec4,0xbf7bbe48,0x3f80,0xbe48bf7b,0x3ec43f6d,0xbf0ebf55,0x3f800000,0xbf0e3f55,0xbec4bf6d,0x3f7b3e48,
0xbf353f35,0xbe48bf7b,0x3f6d3ec4,0xbf553f0e,0x80003f80,0xbf55bf0e,0x3f6dbec4,0xbe483f7b,0xbf35bf35,0x3f7bbe48,0xbec43f6d,0xbf0ebf55,
0xbf800000,0x3f0ebf55,0x3ec43f6d,0xbf7bbe48,0x3f35bf35,0x3e483f7b,0xbf6dbec4,0x3f55bf0e,0x8000bf80,0x3f553f0e,0xbf6d3ec4,0x3e48bf7b,
0x3f353f35,0xbf7b3e48,0x3ec4bf6d,0x3f0e3f55,0x3f353f35,0xbf7b3e48,0x3ec4bf6d,0x3f0e3f55,0xbf80,0x3f553f0e,0xbf6d3ec4,0x3e48bf7b,
0xbf353f35,0xbe48bf7b,0x3f6d3ec4,0xbf553f0e,0x3f800000,0xbf0e3f55,0xbec4bf6d,0x3f7b3e48,0xbf35bf35,0x3f7bbe48,0xbec43f6d,0xbf0ebf55,
0x3f80,0xbf55bf0e,0x3f6dbec4,0xbe483f7b,0x3f35bf35,0x3e483f7b,0xbf6dbec4,0x3f55bf0e,0xbf800000,0x3f0ebf55,0x3ec43f6d,0xbf7bbe48,
0x8000bf80,0x3f7bbe48,0x3ec43f6d,0xbf553f0e,0xbf35bf35,0x3f0ebf55,0x3f6d3ec4,0xbe483f7b,0xbf800000,0xbe48bf7b,0x3f6dbec4,0x3f0e3f55,
0xbf353f35,0xbf55bf0e,0x3ec4bf6d,0x3f7b3e48,0x80003f80,0xbf7b3e48,0xbec4bf6d,0x3f55bf0e,0x3f353f35,0xbf0e3f55,0xbf6dbec4,0x3e48bf7b,
0x3f800000,0x3e483f7b,0xbf6d3ec4,0xbf0ebf55,0x3f35bf35,0x3f553f0e,0xbec43f6d,0xbf7bbe48,0xbf353f35,0xbf55bf0e,0x3ec4bf6d,0x3f7b3e48,
0xbf800000,0xbe48bf7b,0x3f6dbec4,0x3f0e3f55,0x3f353f35,0xbf0e3f55,0xbf6dbec4,0x3e48bf7b,0x3f80,0xbf7b3e48,0xbec4bf6d,0x3f55bf0e,
0x3f35bf35,0x3f553f0e,0xbec43f6d,0xbf7bbe48,0x3f800000,0x3e483f7b,0xbf6d3ec4,0xbf0ebf55,0xbf35bf35,0x3f0ebf55,0x3f6d3ec4,0xbe483f7b,
0xbf80,0x3f7bbe48,0x3ec43f6d,0xbf553f0e,0xbf800000,0xbf55bf0e,0xbec4bf6d,0x3e48bf7b,0x3f35bf35,0x3f7bbe48,0x3f6d3ec4,0x3f0e3f55,
0x8000bf80,0x3f0ebf55,0x3f6dbec4,0x3f7b3e48,0x3f353f35,0x3e483f7b,0xbec43f6d,0xbf553f0e,0x3f800000,0x3f553f0e,0x3ec43f6d,0xbe483f7b,
0xbf353f35,0xbf7b3e48,0xbf6dbec4,0xbf0ebf55,0x80003f80,0xbf0e3f55,0xbf6d3ec4,0xbf7bbe48,0xbf35bf35,0xbe48bf7b,0x3ec4bf6d,0x3f55bf0e,
0xbf35bf35,0xbe48bf7b,0x3ec4bf6d,0x3f55bf0e,0x3f80,0xbf0e3f55,0xbf6d3ec4,0xbf7bbe48,0x3f35bf35,0x3f7bbe48,0x3f6d3ec4,0x3f0e3f55,
0xbf800000,0xbf55bf0e,0xbec4bf6d,0x3e48bf7b,0x3f353f35,0x3e483f7b,0xbec43f6d,0xbf553f0e,0xbf80,0x3f0ebf55,0x3f6dbec4,0x3f7b3e48,
0xbf353f35,0xbf7b3e48,0xbf6dbec4,0xbf0ebf55,0x3f800000,0x3f553f0e,0x3ec43f6d,0xbe483f7b,0x80003f80,0xbec4bf6d,0x3f353f35,0xbf6dbec4,
0x3f800000,0xbf6d3ec4,0x3f35bf35,0xbec43f6d,0x8000bf80,0x3ec43f6d,0xbf35bf35,0x3f6d3ec4,0xbf800000,0x3f6dbec4,0xbf353f35,0x3ec4bf6d,
0x80003f80,0xbec4bf6d,0x3f353f35,0xbf6dbec4,0x3f800000,0xbf6d3ec4,0x3f35bf35,0xbec43f6d,0x8000bf80,0x3ec43f6d,0xbf35bf35,0x3f6d3ec4,
0xbf800000,0x3f6dbec4,0xbf353f35,0x3ec4bf6d,0xbf80,0x3ec43f6d,0xbf35bf35,0x3f6d3ec4,0x3f800000,0xbf6d3ec4,0x3f35bf35,0xbec43f6d,
0x3f80,0xbec4bf6d,0x3f353f35,0xbf6dbec4,0xbf800000,0x3f6dbec4,0xbf353f35,0x3ec4bf6d,0xbf80,0x3ec43f6d,0xbf35bf35,0x3f6d3ec4,
0x3f800000,0xbf6d3ec4,0x3f35bf35,0xbec43f6d,0x3f80,0xbec4bf6d,0x3f353f35,0xbf6dbec4,0xbf800000,0x3f6dbec4,0xbf353f35,0x3ec4bf6d,
0x8000bf80,0x3f6d3ec4,0xbf353f35,0xbec4bf6d,0x3f800000,0xbec43f6d,0xbf35bf35,0x3f6dbec4,0x80003f80,0xbf6dbec4,0x3f35bf35,0x3ec43f6d,
0xbf800000,0x3ec4bf6d,0x3f353f35,0xbf6d3ec4,0x8000bf80,0x3f6d3ec4,0xbf353f35,0xbec4bf6d,0x3f800000,0xbec43f6d,0xbf35bf35,0x3f6dbec4,
0x80003f80,0xbf6dbec4,0x3f35bf35,0x3ec43f6d,0xbf800000,0x3ec4bf6d,0x3f353f35,0xbf6d3ec4,0xbf80,0x3f6d3ec4,0xbf353f35,0xbec4bf6d,
0xbf800000,0x3ec4bf6d,0x3f353f35,0xbf6d3ec4,0x3f80,0xbf6dbec4,0x3f35bf35,0x3ec43f6d,0x3f800000,0xbec43f6d,0xbf35bf35,0x3f6dbec4,
0xbf80,0x3f6d3ec4,0xbf353f35,0xbec4bf6d,0xbf800000,0x3ec4bf6d,0x3f353f35,0xbf6d3ec4,0x3f80,0xbf6dbec4,0x3f35bf35,0x3ec43f6d,
0x3f800000,0xbec43f6d,0xbf35bf35,0x3f6dbec4,0x80003f80,0xbf6d3ec4,0xbf35bf35,0x3ec4bf6d,0x3f800000,0x3ec43f6d,0xbf353f35,0xbf6dbec4,
0x8000bf80,0x3f6dbec4,0x3f353f35,0xbec43f6d,0xbf800000,0xbec4bf6d,0x3f35bf35,0x3f6d3ec4,0x80003f80,0xbf6d3ec4,0xbf35bf35,0x3ec4bf6d,
0x3f800000,0x3ec43f6d,0xbf353f35,0xbf6dbec4,0x8000bf80,0x3f6dbec4,0x3f353f35,0xbec43f6d,0xbf800000,0xbec4bf6d,0x3f35bf35,0x3f6d3ec4,
0xbf80,0x3f6dbec4,0x3f353f35,0xbec43f6d,0x3f800000,0x3ec43f6d,0xbf353f35,0xbf6dbec4,0x3f80,0xbf6d3ec4,0xbf35bf35,0x3ec4bf6d,
0xbf800000,0xbec4bf6d,0x3f35bf35,0x3f6d3ec4,0xbf80,0x3f6dbec4,0x3f353f35,0xbec43f6d,0x3f800000,0x3ec43f6d,0xbf353f35,0xbf6dbec4,
0x3f80,0xbf6d3ec4,0xbf35bf35,0x3ec4bf6d,0xbf800000,0xbec4bf6d,0x3f35bf35,0x3f6d3ec4,0x8000bf80,0x3ec4bf6d,0x3f35bf35,0x3f6dbec4,
0x3f800000,0x3f6d3ec4,0x3f353f35,0x3ec43f6d,0x80003f80,0xbec43f6d,0xbf353f35,0xbf6d3ec4,0xbf800000,0xbf6dbec4,0xbf35bf35,0xbec4bf6d,
0x8000bf80,0x3ec4bf6d,0x3f35bf35,0x3f6dbec4,0x3f800000,0x3f6d3ec4,0x3f353f35,0x3ec43f6d,0x80003f80,0xbec43f6d,0xbf353f35,0xbf6d3ec4,
0xbf800000,0xbf6dbec4,0xbf35bf35,0xbec4bf6d,0xbf80,0x3ec4bf6d,0x3f35bf35,0x3f6dbec4,0xbf800000,0xbf6dbec4,0xbf35bf35,0xbec4bf6d,
0x3f80,0xbec43f6d,0xbf353f35,0xbf6d3ec4,0x3f800000,0x3f6d3ec4,0x3f353f35,0x3ec43f6d,0xbf80,0x3ec4bf6d,0x3f35bf35,0x3f6dbec4,
0xbf800000,0xbf6dbec4,0xbf35bf35,0xbec4bf6d,0x3f80,0xbec43f6d,0xbf353f35,0xbf6d3ec4,0x3f800000,0x3f6d3ec4,0x3f353f35,0x3ec43f6d,
0x80003f80,0xbf0ebf55,0x3f6d3ec4,0xbf7b3e48,0x3f35bf35,0xbe483f7b,0xbec4bf6d,0x3f553f0e,0xbf800000,0x3f55bf0e,0xbec43f6d,0xbe48bf7b,
0x3f353f35,0xbf7bbe48,0x3f6dbec4,0xbf0e3f55,0x8000bf80,0x3f0e3f55,0xbf6dbec4,0x3f7bbe48,0xbf353f35,0x3e48bf7b,0x3ec43f6d,0xbf55bf0e,
0x3f800000,0xbf553f0e,0x3ec4bf6d,0x3e483f7b,0xbf35bf35,0x3f7b3e48,0xbf6d3ec4,0x3f0ebf55,0xbf35bf35,0x3f7b3e48,0xbf6d3ec4,0x3f0ebf55,
0x3f800000,0xbf553f0e,0x3ec4bf6d,0x3e483f7b,0x3f35bf35,0xbe483f7b,0xbec4bf6d,0x3f553f0e,0x3f80,0xbf0ebf55,0x3f6d3ec4,0xbf7b3e48,
0x3f353f35,0xbf7bbe48,0x3f6dbec4,0xbf0e3f55,0xbf800000,0x3f55bf0e,0xbec43f6d,0xbe48bf7b,0xbf353f35,0x3e48bf7b,0x3ec43f6d,0xbf55bf0e,
0xbf80,0x3f0e3f55,0xbf6dbec4,0x3f7bbe48,0xbf800000,0x3e48bf7b,0x3f6d3ec4,0xbf0e3f55,0xbf35bf35,0x3f55bf0e,0x3ec43f6d,0xbf7b3e48,
0x80003f80,0xbf7bbe48,0x3ec4bf6d,0x3f553f0e,0xbf353f35,0xbf0ebf55,0x3f6dbec4,0x3e483f7b,0x3f800000,0xbe483f7b,0xbf6dbec4,0x3f0ebf55,
0x3f353f35,0xbf553f0e,0xbec4bf6d,0x3f7bbe48,0x8000bf80,0x3f7b3e48,0xbec43f6d,0xbf55bf0e,0x3f35bf35,0x3f0e3f55,0xbf6d3ec4,0xbe48bf7b,
0xbf353f35,0xbf0ebf55,0x3f6dbec4,0x3e483f7b,0x3f80,0xbf7bbe48,0x3ec4bf6d,0x3f553f0e,0x3f353f35,0xbf553f0e,0xbec4bf6d,0x3f7bbe48,
0x3f800000,0xbe483f7b,0xbf6dbec4,0x3f0ebf55,0x3f35bf35,0x3f0e3f55,0xbf6d3ec4,0xbe48bf7b,0xbf80,0x3f7b3e48,0xbec43f6d,0xbf55bf0e,
0xbf35bf35,0x3f55bf0e,0x3ec43f6d,0xbf7b3e48,0xbf800000,0x3e48bf7b,0x3f6d3ec4,0xbf0e3f55,0x8000bf80,0x3f55bf0e,0x3f6d3ec4,0x3e483f7b,
0xbf353f35,0xbf7bbe48,0xbec4bf6d,0x3f0ebf55,0x3f800000,0x3f0e3f55,0xbec43f6d,0xbf7b3e48,0xbf35bf35,0x3e48bf7b,0x3f6dbec4,0x3f553f0e,
0x80003f80,0xbf553f0e,0xbf6dbec4,0xbe48bf7b,0x3f35bf35,0x3f7b3e48,0x3ec43f6d,0xbf0e3f55,0xbf800000,0xbf0ebf55,0x3ec4bf6d,0x3f7bbe48,
0x3f353f35,0xbe483f7b,0xbf6d3ec4,0xbf55bf0e,0x3f353f35,0xbe483f7b,0xbf6d3ec4,0xbf55bf0e,0xbf800000,0xbf0ebf55,0x3ec4bf6d,0x3f7bbe48,
0xbf353f35,0xbf7bbe48,0xbec4bf6d,0x3f0ebf55,0xbf80,0x3f55bf0e,0x3f6d3ec4,0x3e483f7b,0xbf35bf35,0x3e48bf7b,0x3f6dbec4,0x3f553f0e,
0x3f800000,0x3f0e3f55,0xbec43f6d,0xbf7b3e48,0x3f35bf35,0x3f7b3e48,0x3ec43f6d,0xbf0e3f55,0x3f80,0xbf553f0e,0xbf6dbec4,0xbe48bf7b,
0x3f800000,0x3f7b3e48,0x3f6d3ec4,0x3f553f0e,0x3f353f35,0x3f0e3f55,0x3ec43f6d,0x3e483f7b,0x8000bf80,0x3e48bf7b,0x3ec4bf6d,0x3f0ebf55,
0x3f35bf35,0x3f55bf0e,0x3f6dbec4,0x3f7bbe48,0xbf800000,0xbf7bbe48,0xbf6dbec4,0xbf55bf0e,0xbf35bf35,0xbf0ebf55,0xbec4bf6d,0xbe48bf7b,
0x80003f80,0xbe483f7b,0xbec43f6d,0xbf0e3f55,0xbf353f35,0xbf553f0e,0xbf6d3ec4,0xbf7b3e48,0x3f35bf35,0x3f55bf0e,0x3f6dbec4,0x3f7bbe48,
0xbf80,0x3e48bf7b,0x3ec4bf6d,0x3f0ebf55,0xbf35bf35,0xbf0ebf55,0xbec4bf6d,0xbe48bf7b,0xbf800000,0xbf7bbe48,0xbf6dbec4,0xbf55bf0e,
0xbf353f35,0xbf553f0e,0xbf6d3ec4,0xbf7b3e48,0x3f80,0xbe483f7b,0xbec43f6d,0xbf0e3f55,0x3f353f35,0x3f0e3f55,0x3ec43f6d,0x3e483f7b,
0x3f800000,0x3f7b3e48,0x3f6d3ec4,0x3f553f0e,
};
__device__ __align__(128) const uint32_t T_TWA[2048] = {
0x3f800000,0x0,0x3f800000,0x0,0x3f800000,0x0,0x3f800000,0x0,0x3f800000,0x0,0x3f800000,0x0,
0x3f800000,0x0,0x3f800000,0x0,0x3f800000,0x0,0x3f7fec43,0xbcc90ab0,0x3f7ffec4,0xbbc90f88,0x3f7fe129,0xbcfb49ba,
0x3f7ffb11,0xbc490e90,0x3f7fd397,0xbd16c32c,0x3f7ff4e6,0xbc96c9b6,0x3f7fc38f,0xbd2fe007,0x3f800000,0x0,0x3f7fb10f,0xbd48fb30,
0x3f7ffb11,0xbc490e90,0x3f7f84ab,0xbd7b2b74,0x3f7fec43,0xbcc90ab0,0x3f7f4e6d,0xbd96a905,0x3f7fd397,0xbd16c32c,0x3f7f0e58,0xbdafb680,
0x3f800000,0x0,0x3f7f4e6d,0xbd96a905,0x3f7ff4e6,0xbc96c9b6,0x3f7eea9d,0xbdbc3ac3,0x3f7fd397,0xbd16c32c,0x3f7e70b0,0xbde1bc2e,
0x3f7f9c18,0xbd621469,0x3f7de0b1,0xbe039502,0x3f800000,0x0,0x3f7ec46d,0xbdc8bd36,0x3f7fec43,0xbcc90ab0,0x3f7e1324,0xbdfab273,
0x3f7fb10f,0xbd48fb30,0x3f7d3aac,0xbe164083,0x3f7f4e6d,0xbd96a905,0x3f7c3b28,0xbe2f10a2,0x3f800000,0x0,0x3f7e1324,0xbdfab273,
0x3f7fe129,0xbcfb49ba,0x3f7cfe73,0xbe1c76de,0x3f7f84ab,0xbd7b2b74,0x3f7baccd,0xbe3b6ecf,0x3f7eea9d,0xbdbc3ac3,0x3f7a1e84,0xbe5a3997,
0x3f800000,0x0,0x3f7d3aac,0xbe164083,0x3f7fd397,0xbd16c32c,0x3f7baccd,0xbe3b6ecf,0x3f7f4e6d,0xbd96a905,0x3f79c79d,0xbe605c13,
0x3f7e70b0,0xbde1bc2e,0x3f778bc5,0xbe827dc0,0x3f800000,0x0,0x3f7c3b28,0xbe2f10a2,0x3f7fc38f,0xbd2fe007,0x3f7a1e84,0xbe5a3997,
0x3f7f0e58,0xbdafb680,0x3f778bc5,0xbe827dc0,0x3f7de0b1,0xbe039502,0x3f748422,0xbe97a117,0x3f800000,0x0,0x3f7b14be,0xbe47c5c2,
0x3f7fb10f,0xbd48fb30,0x3f7853f8,0xbe78cfcc,0x3f7ec46d,0xbdc8bd36,0x3f74fa0b,0xbe94a031,0x3f7d3aac,0xbe164083,0x3f710908,0xbeac7cd4,
0x3f800000,0x0,0x3f79c79d,0xbe605c13,0x3f7f9c18,0xbd621469,0x3f764d97,0xbe8b9507,0x3f7e70b0,0xbde1bc2e,0x3f721352,0xbea68f12,
0x3f7c7eb0,0xbe28defc,0x3f6d1c1d,0xbec1071e,0x3f800000,0x0,0x3f7853f8,0xbe78cfcc,0x3f7f84ab,0xbd7b2b74,0x3f740bdd,0xbe9aa086,
0x3f7e1324,0xbdfab273,0x3f6ed89e,0xbeb8442a,0x3f7baccd,0xbe3b6ecf,0x3f68bf3c,0xbed53641,0x3f800000,0x0,0x3f76ba07,0xbe888e93,
0x3f7f6ac7,0xbd8a200a,0x3f718f57,0xbea986c4,0x3f7dabcc,0xbe09cf86,0x3f6b4b0c,0xbec9b953,0x3f7ac516,0xbe4dee60,0x3f63f473,0xbee900b7,
0x3f800000,0x0,0x3f74fa0b,0xbe94a031,0x3f7f4e6d,0xbd96a905,0x3f6ed89e,0xbeb8442a,0x3f7d3aac,0xbe164083,0x3f676bd8,0xbedae880,
0x3f79c79d,0xbe605c13,0x3f5ebe05,0xbefc5d27,0x3f800000,0x0,0x3f731447,0xbea09ae5,0x3f7f2f9d,0xbda3308c,0x3f6be858,0xbec6d529,
0x3f7cbfc9,0xbe22abb6,0x3f633c5a,0xbeebcbbb,0x3f78b47b,0xbe72b651,0x3f591e6a,0xbf07a136,0x3f800000,0x0,0x3f710908,0xbeac7cd4,
0x3f7f0e58,0xbdafb680,0x3f68bf3c,0xbed53641,0x3f7c3b28,0xbe2f10a2,0x3f5ebe05,0xbefc5d27,0x3f778bc5,0xbe827dc0,0x3f531849,0xbf10d3cd,
0x3f800000,0x0,0x3f6ed89e,0xbeb8442a,0x3f7eea9d,0xbdbc3ac3,0x3f655e0b,0xbee363fa,0x3f7baccd,0xbe3b6ecf,0x3f59f26a,0xbf064b82,
0x3f764d97,0xbe8b9507,0x3f4cae79,0xbf19c200,0x3f800000,0x0,0x3f6c835e,0xbec3ef15,0x3f7ec46d,0xbdc8bd36,0x3f61c598,0xbef15aea,
0x3f7b14be,0xbe47c5c2,0x3f54db31,0xbf0e39da,0x3f74fa0b,0xbe94a031,0x3f45e403,0xbf226799,0x3f800000,0x0,0x3f6a09a7,0xbecf7bca,
0x3f7e9bc9,0xbdd53db9,0x3f5df6be,0xbeff17b2,0x3f7a7302,0xbe541501,0x3f4f7a1f,0xbf15f6d9,0x3f73913f,0xbe9d9e78,0x3f3ebc1b,0xbf2ac082,
0x3f800000,0x0,0x3f676bd8,0xbedae880,0x3f7e70b0,0xbde1bc2e,0x3f59f26a,0xbf064b82,0x3f79c79d,0xbe605c13,0x3f49d112,0xbf1d7fd1,
0x3f721352,0xbea68f12,0x3f373a23,0xbf32c8c9,0x3f800000,0x0,0x3f64aa59,0xbee63375,0x3f7e4323,0xbdee3876,0x3f55b993,0xbf0cead0,
0x3f791298,0xbe6c9a7f,0x3f43e200,0xbf24d225,0x3f708066,0xbeaf713a,0x3f2f61a5,0xbf3a7ca4,0x3f800000,0x0,0x3f61c598,0xbef15aea,
0x3f7e1324,0xbdfab273,0x3f514d3d,0xbf13682a,0x3f7853f8,0xbe78cfcc,0x3f3daef9,0xbf2beb4a,0x3f6ed89e,0xbeb8442a,0x3f273656,0xbf41d870,
0x3f800000,0x0,0x3f5ebe05,0xbefc5d27,0x3f7de0b1,0xbe039502,0x3f4cae79,0xbf19c200,0x3f778bc5,0xbe827dc0,0x3f373a23,0xbf32c8c9,
0x3f6d1c1d,0xbec1071e,0x3f1ebc12,0xbf48d8b3,0x3f800000,0x0,0x3f5b941a,0xbf039c3d,0x3f7dabcc,0xbe09cf86,0x3f47de65,0xbf1ff6cb,
0x3f76ba07,0xbe888e93,0x3f3085bb,0xbf396842,0x3f6b4b0c,0xbec9b953,0x3f15f6d9,0xbf4f7a1f,0x3f800000,0x0,0x3f584853,0xbf08f59b,
0x3f7d7474,0xbe1008b7,0x3f42de29,0xbf26050a,0x3f75dec6,0xbe8e9a22,0x3f299415,0xbf3fc767,0x3f696591,0xbed25a09,0x3f0cead0,0xbf55b993,
0x3f800000,0x0,0x3f54db31,0xbf0e39da,0x3f7d3aac,0xbe164083,0x3f3daef9,0xbf2beb4a,0x3f74fa0b,0xbe94a031,0x3f226799,0xbf45e403,
0x3f676bd8,0xbedae880,0x3f039c3d,0xbf5b941a,0x3f800000,0x0,0x3f514d3d,0xbf13682a,0x3f7cfe73,0xbe1c76de,0x3f385216,0xbf31a81d,
0x3f740bdd,0xbe9aa086,0x3f1b02c6,0xbf4bbbf8,0x3f655e0b,0xbee363fa,0x3ef41f07,0xbf6106f2,0x3f800000,0x0,0x3f4d9f02,0xbf187fc0,
0x3f7cbfc9,0xbe22abb6,0x3f32c8c9,0xbf373a23,0x3f731447,0xbea09ae5,0x3f13682a,0xbf514d3d,0x3f633c5a,0xbeebcbbb,0x3ee0924f,0xbf660f88,
0x3f800000,0x0,0x3f49d112,0xbf1d7fd1,0x3f7c7eb0,0xbe28defc,0x3f2d1469,0xbf3ca003,0x3f721352,0xbea68f12,0x3f0b9a6b,0xbf5695e5,
0x3f6106f2,0xbef41f07,0x3ecc9b8b,0xbf6aab7b,0x3f800000,0x0,0x3f45e403,0xbf226799,0x3f7c3b28,0xbe2f10a2,0x3f273656,0xbf41d870,
0x3f710908,0xbeac7cd4,0x3f039c3d,0xbf5b941a,0x3f5ebe05,0xbefc5d27,0x3eb8442a,0xbf6ed89e,0x3f800000,0x0,0x3f41d870,0xbf273656,
0x3f7bf531,0xbe354098,0x3f212ff9,0xbf46e22a,0x3f6ff573,0xbeb263ef,0x3ef6e0cb,0xbf604621,0x3f5c61c7,0xbf0242b1,0x3ea395c5,0xbf7294f8,
0x3f800000,0x0,0x3f3daef9,0xbf2beb4a,0x3f7baccd,0xbe3b6ecf,0x3f1b02c6,0xbf4bbbf8,0x3f6ed89e,0xbeb8442a,0x3ee63375,0xbf64aa59,
0x3f59f26a,0xbf064b82,0x3e8e9a22,0xbf75dec6,0x3f800000,0x0,0x3f396842,0xbf3085bb,0x3f7b61fc,0xbe419b37,0x3f14b039,0xbf5064af,
0x3f6db293,0xbebe1d4a,0x3ed53641,0xbf68bf3c,0x3f577026,0xbf0a48ad,0x3e72b651,0xbf78b47b,0x3f800000,0x0,0x3f800000,0x0,
0x3f800000,0x0,0x3f800000,0x0,0x3f800000,0x0,0x3f800000,0x0,0x3f800000,0x0,0x3f800000,0x0,
0x3f7fb10f,0xbd48fb30,0x3f7f4e6d,0xbd96a905,0x3f7f9c18,0xbd621469,0x3f7f2f9d,0xbda3308c,0x3f7f84ab,0xbd7b2b74,0x3f7f0e58,0xbdafb680,
0x3f7f6ac7,0xbd8a200a,0x3f7eea9d,0xbdbc3ac3,0x3f7ec46d,0xbdc8bd36,0x3f7d3aac,0xbe164083,0x3f7e70b0,0xbde1bc2e,0x3f7cbfc9,0xbe22abb6,
0x3f7e1324,0xbdfab273,0x3f7c3b28,0xbe2f10a2,0x3f7dabcc,0xbe09cf86,0x3f7baccd,0xbe3b6ecf,0x3f7d3aac,0xbe164083,0x3f79c79d,0xbe605c13,
0x3f7c7eb0,0xbe28defc,0x3f78b47b,0xbe72b651,0x3f7baccd,0xbe3b6ecf,0x3f778bc5,0xbe827dc0,0x3f7ac516,0xbe4dee60,0x3f764d97,0xbe8b9507,
0x3f7b14be,0xbe47c5c2,0x3f74fa0b,0xbe94a031,0x3f79c79d,0xbe605c13,0x3f731447,0xbea09ae5,0x3f7853f8,0xbe78cfcc,0x3f710908,0xbeac7cd4,
0x3f76ba07,0xbe888e93,0x3f6ed89e,0xbeb8442a,0x3f7853f8,0xbe78cfcc,0x3f6ed89e,0xbeb8442a,0x3f764d97,0xbe8b9507,0x3f6be858,0xbec6d529,
0x3f740bdd,0xbe9aa086,0x3f68bf3c,0xbed53641,0x3f718f57,0xbea986c4,0x3f655e0b,0xbee363fa,0x3f74fa0b,0xbe94a031,0x3f676bd8,0xbedae880,
0x3f721352,0xbea68f12,0x3f633c5a,0xbeebcbbb,0x3f6ed89e,0xbeb8442a,0x3f5ebe05,0xbefc5d27,0x3f6b4b0c,0xbec9b953,0x3f59f26a,0xbf064b82,
0x3f710908,0xbeac7cd4,0x3f5ebe05,0xbefc5d27,0x3f6d1c1d,0xbec1071e,0x3f591e6a,0xbf07a136,0x3f68bf3c,0xbed53641,0x3f531849,0xbf10d3cd,
0x3f63f473,0xbee900b7,0x3f4cae79,0xbf19c200,0x3f6c835e,0xbec3ef15,0x3f54db31,0xbf0e39da,0x3f676bd8,0xbedae880,0x3f4d9f02,0xbf187fc0,
0x3f61c598,0xbef15aea,0x3f45e403,0xbf226799,0x3f5b941a,0xbf039c3d,0x3f3daef9,0xbf2beb4a,0x3f676bd8,0xbedae880,0x3f49d112,0xbf1d7fd1,
0x3f6106f2,0xbef41f07,0x3f40d0da,0xbf286605,0x3f59f26a,0xbf064b82,0x3f373a23,0xbf32c8c9,0x3f5233c6,0xbf121eb0,0x3f2d1469,0xbf3ca003,
0x3f61c598,0xbef15aea,0x3f3daef9,0xbf2beb4a,0x3f59f26a,0xbf064b82,0x3f32c8c9,0xbf373a23,0x3f514d3d,0xbf13682a,0x3f273656,0xbf41d870,
0x3f47de65,0xbf1ff6cb,0x3f1b02c6,0xbf4bbbf8,0x3f5b941a,0xbf039c3d,0x3f3085bb,0xbf396842,0x3f5233c6,0xbf121eb0,0x3f239da9,0xbf44e3f5,
0x3f47de65,0xbf1ff6cb,0x3f15f6d9,0xbf4f7a1f,0x3f3ca003,0xbf2d1469,0x3f07a136,0xbf591e6a,0x3f54db31,0xbf0e39da,0x3f226799,0xbf45e403,
0x3f49d112,0xbf1d7fd1,0x3f13682a,0xbf514d3d,0x3f3daef9,0xbf2beb4a,0x3f039c3d,0xbf5b941a,0x3f3085bb,0xbf396842,0x3ee63375,0xbf64aa59,
0x3f4d9f02,0xbf187fc0,0x3f13682a,0xbf514d3d,0x3f40d0da,0xbf286605,0x3f0242b1,0xbf5c61c7,0x3f32c8c9,0xbf373a23,0x3ee0924f,0xbf660f88,
0x3f239da9,0xbf44e3f5,0x3ebb31a0,0xbf6e46be,0x3f45e403,0xbf226799,0x3f039c3d,0xbf5b941a,0x3f373a23,0xbf32c8c9,0x3ee0924f,0xbf660f88,
0x3f273656,0xbf41d870,0x3eb8442a,0xbf6ed89e,0x3f15f6d9,0xbf4f7a1f,0x3e8e9a22,0xbf75dec6,0x3f3daef9,0xbf2beb4a,0x3ee63375,0xbf64aa59,
0x3f2d1469,0xbf3ca003,0x3ebb31a0,0xbf6e46be,0x3f1b02c6,0xbf4bbbf8,0x3e8e9a22,0xbf75dec6,0x3f07a136,0xbf591e6a,0x3e419b37,0xbf7b61fc,
0x3f3504f3,0xbf3504f3,0x3ec3ef15,0xbf6c835e,0x3f226799,0xbf45e403,0x3e94a031,0xbf74fa0b,0x3f0e39da,0xbf54db31,0x3e47c5c2,0xbf7b14be,
0x3ef15aea,0xbf61c598,0x3dc8bd36,0xbf7ec46d,0x3f2beb4a,0xbf3daef9,0x3ea09ae5,0xbf731447,0x3f173c07,0xbf4e8d90,0x3e5a3997,0xbf7a1e84,
0x3f00e7e4,0xbf5d2d53,0x3de1bc2e,0xbf7e70b0,0x3ed25a09,0xbf696591,0x3bc90f88,0xbf7ffec4,0x3f226799,0xbf45e403,0x3e78cfcc,0xbf7853f8,
0x3f0b9a6b,0xbf5695e5,0x3e09cf86,0xbf7dabcc,0x3ee63375,0xbf64aa59,0x3cc90ab0,0xbf7fec43,0x3eb263ef,0xbf6ff573,0xbdafb680,0xbf7f0e58,
0x3f187fc0,0xbf4d9f02,0x3e2f10a2,0xbf7c3b28,0x3eff17b2,0xbf5df6be,0x3d621469,0xbf7f9c18,0x3ec9b953,0xbf6b4b0c,0xbd7b2b74,0xbf7f84ab,
0x3e919ddd,0xbf756d97,0xbe354098,0xbf7bf531,0x3f0e39da,0xbf54db31,0x3dc8bd36,0xbf7ec46d,0x3ee63375,0xbf64aa59,0xbcc90ab0,0xbf7fec43,
0x3eac7cd4,0xbf710908,0xbe164083,0xbf7d3aac,0x3e605c13,0xbf79c79d,0xbe888e93,0xbf76ba07,0x3f039c3d,0xbf5b941a,0x3cc90ab0,0xbf7fec43,
0x3ecc9b8b,0xbf6aab7b,0xbdd53db9,0xbf7e9bc9,0x3e8e9a22,0xbf75dec6,0xbe6c9a7f,0xbf791298,0x3e1c76de,0xbf7cfe73,0xbeb554ec,0xbf6f6830,
0x3ef15aea,0xbf61c598,0xbd48fb30,0xbf7fb10f,0x3eb263ef,0xbf6ff573,0xbe3b6ecf,0xbf7baccd,0x3e605c13,0xbf79c79d,0xbea09ae5,0xbf731447,
0x3dafb680,0xbf7f0e58,0xbee0924f,0xbf660f88,0x3edae880,0xbf676bd8,0xbdfab273,0xbf7e1324,0x3e97a117,0xbf748422,0xbe8586ce,0xbf772417,
0x3e22abb6,0xbf7cbfc9,0xbec9b953,0xbf6b4b0c,0x3c96c9b6,0xbf7ff4e6,0xbf04f484,0xbf5ac450,0x3ec3ef15,0xbf6c835e,0xbe47c5c2,0xbf7b14be,
0x3e78cfcc,0xbf7853f8,0xbeac7cd4,0xbf710908,0x3dc8bd36,0xbf7ec46d,0xbef15aea,0xbf61c598,0xbd48fb30,0xbf7fb10f,0xbf187fc0,0xbf4d9f02,
0x3eac7cd4,0xbf710908,0xbe888e93,0xbf76ba07,0x3e419b37,0xbf7b61fc,0xbed25a09,0xbf696591,0x3d16c32c,0xbf7fd397,0xbf0b9a6b,0xbf5695e5,
0xbdee3876,0xbf7e4323,0xbf2ac082,0xbf3ebc1b,0x3e94a031,0xbf74fa0b,0xbeac7cd4,0xbf710908,0x3e09cf86,0xbf7dabcc,0xbef6e0cb,0xbf604621,
0xbcc90ab0,0xbf7fec43,0xbf1d7fd1,0xbf49d112,0xbe3b6ecf,0xbf7baccd,0xbf3b8f3b,0xbf2e3bde,0x3e78cfcc,0xbf7853f8,0xbecf7bca,0xbf6a09a7,
0x3da3308c,0xbf7f2f9d,0xbf0cead0,0xbf55b993,0xbdafb680,0xbf7f0e58,0xbf2e3bde,0xbf3b8f3b,0xbe7ee6e1,0xbf77f110,0xbf4ac77f,0xbf1c420c,
0x3e47c5c2,0xbf7b14be,0xbef15aea,0xbf61c598,0x3cc90ab0,0xbf7fec43,0xbf1d7fd1,0xbf49d112,0xbe164083,0xbf7d3aac,0xbf3daef9,0xbf2beb4a,
0xbea09ae5,0xbf731447,0xbf584853,0xbf08f59b,0x3e164083,0xbf7d3aac,0xbf08f59b,0xbf584853,0xbcfb49ba,0xbf7fe129,0xbf2d1469,0xbf3ca003,
0xbe541501,0xbf7a7302,0xbf4bbbf8,0xbf1b02c6,0xbec1071e,0xbf6d1c1d,0xbf63f473,0xbee900b7,0x3dc8bd36,0xbf7ec46d,0xbf187fc0,0xbf4d9f02,
0xbdafb680,0xbf7f0e58,0xbf3b8f3b,0xbf2e3bde,0xbe888e93,0xbf76ba07,0xbf584853,0xbf08f59b,0xbee0924f,0xbf660f88,0xbf6db293,0xbebe1d4a,
0x3d48fb30,0xbf7fb10f,0xbf273656,0xbf41d870,0xbe1008b7,0xbf7d7474,0xbf48d8b3,0xbf1ebc12,0xbea68f12,0xbf721352,0xbf633c5a,0xbeebcbbb,
0xbeff17b2,0xbf5df6be,0xbf756d97,0xbe919ddd,0x3f800000,0x0,0x3f800000,0x0,0x3f800000,0x0,0x3f800000,0x0,
0x3f800000,0x0,0x3f800000,0x0,0x3f800000,0x0,0x3f800000,0x0,0x3f7ec46d,0xbdc8bd36,0x3f7e1324,0xbdfab273,
0x3f7e9bc9,0xbdd53db9,0x3f7de0b1,0xbe039502,0x3f7e70b0,0xbde1bc2e,0x3f7dabcc,0xbe09cf86,0x3f7e4323,0xbdee3876,0x3f7d7474,0xbe1008b7,
0x3f7b14be,0xbe47c5c2,0x3f7853f8,0xbe78cfcc,0x3f7a7302,0xbe541501,0x3f778bc5,0xbe827dc0,0x3f79c79d,0xbe605c13,0x3f76ba07,0xbe888e93,
0x3f791298,0xbe6c9a7f,0x3f75dec6,0xbe8e9a22,0x3f74fa0b,0xbe94a031,0x3f6ed89e,0xbeb8442a,0x3f73913f,0xbe9d9e78,0x3f6d1c1d,0xbec1071e,
0x3f721352,0xbea68f12,0x3f6b4b0c,0xbec9b953,0x3f708066,0xbeaf713a,0x3f696591,0xbed25a09,0x3f6c835e,0xbec3ef15,0x3f61c598,0xbef15aea,
0x3f6a09a7,0xbecf7bca,0x3f5ebe05,0xbefc5d27,0x3f676bd8,0xbedae880,0x3f5b941a,0xbf039c3d,0x3f64aa59,0xbee63375,0x3f584853,0xbf08f59b,
0x3f61c598,0xbef15aea,0x3f514d3d,0xbf13682a,0x3f5df6be,0xbeff17b2,0x3f4cae79,0xbf19c200,0x3f59f26a,0xbf064b82,0x3f47de65,0xbf1ff6cb,
0x3f55b993,0xbf0cead0,0x3f42de29,0xbf26050a,0x3f54db31,0xbf0e39da,0x3f3daef9,0xbf2beb4a,0x3f4f7a1f,0xbf15f6d9,0x3f373a23,0xbf32c8c9,
0x3f49d112,0xbf1d7fd1,0x3f3085bb,0xbf396842,0x3f43e200,0xbf24d225,0x3f299415,0xbf3fc767,0x3f45e403,0xbf226799,0x3f273656,0xbf41d870,
0x3f3ebc1b,0xbf2ac082,0x3f1ebc12,0xbf48d8b3,0x3f373a23,0xbf32c8c9,0x3f15f6d9,0xbf4f7a1f,0x3f2f61a5,0xbf3a7ca4,0x3f0cead0,0xbf55b993,
0x3f3504f3,0xbf3504f3,0x3f0e39da,0xbf54db31,0x3f2beb4a,0xbf3daef9,0x3f039c3d,0xbf5b941a,0x3f226799,0xbf45e403,0x3ef15aea,0xbf61c598,
0x3f187fc0,0xbf4d9f02,0x3edae880,0xbf676bd8,0x3f226799,0xbf45e403,0x3ee63375,0xbf64aa59,0x3f173c07,0xbf4e8d90,0x3ecc9b8b,0xbf6aab7b,
0x3f0b9a6b,0xbf5695e5,0x3eb263ef,0xbf6ff573,0x3eff17b2,0xbf5df6be,0x3e97a117,0xbf748422,0x3f0e39da,0xbf54db31,0x3eac7cd4,0xbf710908,
0x3f00e7e4,0xbf5d2d53,0x3e8e9a22,0xbf75dec6,0x3ee63375,0xbf64aa59,0x3e605c13,0xbf79c79d,0x3ec9b953,0xbf6b4b0c,0x3e22abb6,0xbf7cbfc9,
0x3ef15aea,0xbf61c598,0x3e605c13,0xbf79c79d,0x3ed25a09,0xbf696591,0x3e1c76de,0xbf7cfe73,0x3eb263ef,0xbf6ff573,0x3dafb680,0xbf7f0e58,
0x3e919ddd,0xbf756d97,0x3c96c9b6,0xbf7ff4e6,0x3ec3ef15,0xbf6c835e,0x3dc8bd36,0xbf7ec46d,0x3ea09ae5,0xbf731447,0x3cc90ab0,0xbf7fec43,
0x3e78cfcc,0xbf7853f8,0xbd48fb30,0xbf7fb10f,0x3e2f10a2,0xbf7c3b28,0xbdfab273,0xbf7e1324,0x3e94a031,0xbf74fa0b,0xbcc90ab0,0xbf7fec43,
0x3e5a3997,0xbf7a1e84,0xbdd53db9,0xbf7e9bc9,0x3e09cf86,0xbf7dabcc,0xbe3b6ecf,0xbf7baccd,0x3d621469,0xbf7f9c18,0xbe8586ce,0xbf772417,
0x3e47c5c2,0xbf7b14be,0xbe164083,0xbf7d3aac,0x3de1bc2e,0xbf7e70b0,0xbe6c9a7f,0xbf791298,0x3cc90ab0,0xbf7fec43,0xbea09ae5,0xbf731447,
0xbd7b2b74,0xbf7f84ab,0xbec9b953,0xbf6b4b0c,0x3dc8bd36,0xbf7ec46d,0xbe888e93,0xbf76ba07,0x3bc90f88,0xbf7ffec4,0xbeb554ec,0xbf6f6830,
0xbdafb680,0xbf7f0e58,0xbee0924f,0xbf660f88,0xbe354098,0xbf7bf531,0xbf04f484,0xbf5ac450,0x0,0xbf800000,0xbec3ef15,0xbf6c835e,
0xbdc8bd36,0xbf7ec46d,0xbef15aea,0xbf61c598,0xbe47c5c2,0xbf7b14be,0xbf0e39da,0xbf54db31,0xbe94a031,0xbf74fa0b,0xbf226799,0xbf45e403,
0xbdc8bd36,0xbf7ec46d,0xbefc5d27,0xbf5ebe05,0xbe4dee60,0xbf7ac516,0xbf14b039,0xbf5064af,0xbe9aa086,0xbf740bdd,0xbf299415,0xbf3fc767,
0xbecc9b8b,0xbf6aab7b,0xbf3ca003,0xbf2d1469,0xbe47c5c2,0xbf7b14be,0xbf187fc0,0xbf4d9f02,0xbe9aa086,0xbf740bdd,0xbf2e3bde,0xbf3b8f3b,
0xbecf7bca,0xbf6a09a7,0xbf41d870,0xbf273656,0xbf00e7e4,0xbf5d2d53,0xbf531849,0xbf10d3cd,0xbe94a031,0xbf74fa0b,0xbf3085bb,0xbf396842,
0xbecc9b8b,0xbf6aab7b,0xbf44e3f5,0xbf239da9,0xbf00e7e4,0xbf5d2d53,0xbf5695e5,0xbf0b9a6b,0xbf19c200,0xbf4cae79,0xbf655e0b,0xbee363fa,
0xbec3ef15,0xbf6c835e,0xbf45e403,0xbf226799,0xbefc5d27,0xbf5ebe05,0xbf584853,0xbf08f59b,0xbf187fc0,0xbf4d9f02,0xbf676bd8,0xbedae880,
0xbf3085bb,0xbf396842,0xbf731447,0xbea09ae5,0xbef15aea,0xbf61c598,0xbf584853,0xbf08f59b,0xbf14b039,0xbf5064af,0xbf6816a8,0xbed8106b,
0xbf2e3bde,0xbf3b8f3b,0xbf740bdd,0xbe9aa086,0xbf44e3f5,0xbf239da9,0xbf7bf531,0xbe354098,0xbf0e39da,0xbf54db31,0xbf676bd8,0xbedae880,
0xbf299415,0xbf3fc767,0xbf740bdd,0xbe9aa086,0xbf41d870,0xbf273656,0xbf7c3b28,0xbe2f10a2,0xbf5695e5,0xbf0b9a6b,0xbf7fd397,0xbd16c32c,
0xbf226799,0xbf45e403,0xbf731447,0xbea09ae5,0xbf3ca003,0xbf2d1469,0xbf7bf531,0xbe354098,0xbf531849,0xbf10d3cd,0xbf7fd397,0xbd16c32c,
0xbf655e0b,0xbee363fa,0xbf7e9bc9,0x3dd53db9,0xbf3504f3,0xbf3504f3,0xbf7b14be,0xbe47c5c2,0xbf4d9f02,0xbf187fc0,0xbf7fb10f,0xbd48fb30,
0xbf61c598,0xbef15aea,0xbf7ec46d,0x3dc8bd36,0xbf710908,0xbeac7cd4,0xbf7853f8,0x3e78cfcc,0xbf45e403,0xbf226799,0xbf7f4e6d,0xbd96a905,
0xbf5c61c7,0xbf0242b1,0xbf7f2f9d,0x3da3308c,0xbf6db293,0xbebe1d4a,0xbf791298,0x3e6c9a7f,0xbf796e4e,0xbe667c66,0xbf6d1c1d,0x3ec1071e,
0xbf54db31,0xbf0e39da,0xbf7fb10f,0x3d48fb30,0xbf68bf3c,0xbed53641,0xbf7a7302,0x3e541501,0xbf76ba07,0xbe888e93,0xbf6ed89e,0x3eb8442a,
0xbf7e70b0,0xbde1bc2e,0xbf5d2d53,0x3f00e7e4,0xbf61c598,0xbef15aea,0xbf7c3b28,0x3e2f10a2,0xbf7294f8,0xbea395c5,0xbf718f57,0x3ea986c4,
0xbf7cbfc9,0xbe22abb6,0xbf604621,0x3ef6e0cb,0xbf7ffec4,0x3bc90f88,0xbf48d8b3,0x3f1ebc12,0xbf6c835e,0xbec3ef15,0xbf74fa0b,0x3e94a031,
0xbf79c79d,0xbe605c13,0xbf64aa59,0x3ee63375,0xbf7fb10f,0xbd48fb30,0xbf4d9f02,0x3f187fc0,0xbf7e1324,0x3dfab273,0xbf3085bb,0x3f396842,
0xbf74fa0b,0xbe94a031,0xbf6a09a7,0x3ecf7bca,0xbf7e4323,0xbdee3876,0xbf53fac3,0x3f0f8784,0xbf7f84ab,0x3d7b2b74,0xbf373a23,0x3f32c8c9,
0xbf78b47b,0x3e72b651,0xbf14b039,0x3f5064af,0xbf7b14be,0xbe47c5c2,0xbf5b941a,0x3f039c3d,0xbf7ffb11,0xbc490e90,0xbf3fc767,0x3f299415,
0xbf7c3b28,0x3e2f10a2,0xbf1d7fd1,0x3f49d112,0xbf6ff573,0x3eb263ef,0xbeebcbbb,0x3f633c5a,0xbf7ec46d,0xbdc8bd36,0xbf49d112,0x3f1d7fd1,
0xbf7eea9d,0x3dbc3ac3,0xbf286605,0x3f40d0da,0xbf75dec6,0x3e8e9a22,0xbf00e7e4,0x3f5d2d53,0xbf63f473,0x3ee900b7,0xbea986c4,0x3f718f57,
0x3f800000,0x0,0x3f800000,0x0,0x3f800000,0x0,0x3f800000,0x0,0x3f800000,0x0,0x3f800000,0x0,
0x3f800000,0x0,0x3f800000,0x0,0x3f7d3aac,0xbe164083,0x3f7c3b28,0xbe2f10a2,0x3f7cfe73,0xbe1c76de,0x3f7bf531,0xbe354098,
0x3f7cbfc9,0xbe22abb6,0x3f7baccd,0xbe3b6ecf,0x3f7c7eb0,0xbe28defc,0x3f7b61fc,0xbe419b37,0x3f74fa0b,0xbe94a031,0x3f710908,0xbeac7cd4,
0x3f740bdd,0xbe9aa086,0x3f6ff573,0xbeb263ef,0x3f731447,0xbea09ae5,0x3f6ed89e,0xbeb8442a,0x3f721352,0xbea68f12,0x3f6db293,0xbebe1d4a,
0x3f676bd8,0xbedae880,0x3f5ebe05,0xbefc5d27,0x3f655e0b,0xbee363fa,0x3f5c61c7,0xbf0242b1,0x3f633c5a,0xbeebcbbb,0x3f59f26a,0xbf064b82,
0x3f6106f2,0xbef41f07,0x3f577026,0xbf0a48ad,0x3f54db31,0xbf0e39da,0x3f45e403,0xbf226799,0x3f514d3d,0xbf13682a,0x3f41d870,0xbf273656,
0x3f4d9f02,0xbf187fc0,0x3f3daef9,0xbf2beb4a,0x3f49d112,0xbf1d7fd1,0x3f396842,0xbf3085bb,0x3f3daef9,0xbf2beb4a,0x3f273656,0xbf41d870,
0x3f385216,0xbf31a81d,0x3f212ff9,0xbf46e22a,0x3f32c8c9,0xbf373a23,0x3f1b02c6,0xbf4bbbf8,0x3f2d1469,0xbf3ca003,0x3f14b039,0xbf5064af,
0x3f226799,0xbf45e403,0x3f039c3d,0xbf5b941a,0x3f1b02c6,0xbf4bbbf8,0x3ef6e0cb,0xbf604621,0x3f13682a,0xbf514d3d,0x3ee63375,0xbf64aa59,
0x3f0b9a6b,0xbf5695e5,0x3ed53641,0xbf68bf3c,0x3f039c3d,0xbf5b941a,0x3eb8442a,0xbf6ed89e,0x3ef41f07,0xbf6106f2,0x3ea395c5,0xbf7294f8,
0x3ee0924f,0xbf660f88,0x3e8e9a22,0xbf75dec6,0x3ecc9b8b,0xbf6aab7b,0x3e72b651,0xbf78b47b,0x3ec3ef15,0xbf6c835e,0x3e47c5c2,0xbf7b14be,
0x3eac7cd4,0xbf710908,0x3e164083,0xbf7d3aac,0x3e94a031,0xbf74fa0b,0x3dc8bd36,0xbf7ec46d,0x3e78cfcc,0xbf7853f8,0x3d48fb30,0xbf7fb10f,
0x3e78cfcc,0xbf7853f8,0x3cc90ab0,0xbf7fec43,0x3e419b37,0xbf7b61fc,0xbcfb49ba,0xbf7fe129,0x3e09cf86,0xbf7dabcc,0xbdafb680,0xbf7f0e58,
0x3da3308c,0xbf7f2f9d,0xbe1008b7,0xbf7d7474,0x3dc8bd36,0xbf7ec46d,0xbe164083,0xbf7d3aac,0x3d16c32c,0xbf7fd397,0xbe541501,0xbf7a7302,
0xbcc90ab0,0xbf7fec43,0xbe888e93,0xbf76ba07,0xbdafb680,0xbf7f0e58,0xbea68f12,0xbf721352,0xbd48fb30,0xbf7fb10f,0xbea09ae5,0xbf731447,
0xbdee3876,0xbf7e4323,0xbec1071e,0xbf6d1c1d,0xbe3b6ecf,0xbf7baccd,0xbee0924f,0xbf660f88,0xbe7ee6e1,0xbf77f110,0xbeff17b2,0xbf5df6be,
0xbe47c5c2,0xbf7b14be,0xbef15aea,0xbf61c598,0xbe888e93,0xbf76ba07,0xbf08f59b,0xbf584853,0xbeac7cd4,0xbf710908,0xbf187fc0,0xbf4d9f02,
0xbecf7bca,0xbf6a09a7,0xbf273656,0xbf41d870,0xbeac7cd4,0xbf710908,0xbf1d7fd1,0xbf49d112,0xbed25a09,0xbf696591,0xbf2d1469,0xbf3ca003,
0xbef6e0cb,0xbf604621,0xbf3b8f3b,0xbf2e3bde,0xbf0cead0,0xbf55b993,0xbf48d8b3,0xbf1ebc12,0xbef15aea,0xbf61c598,0xbf3daef9,0xbf2beb4a,
0xbf0b9a6b,0xbf5695e5,0xbf4bbbf8,0xbf1b02c6,0xbf1d7fd1,0xbf49d112,0xbf584853,0xbf08f59b,0xbf2e3bde,0xbf3b8f3b,0xbf633c5a,0xbeebcbbb,
0xbf187fc0,0xbf4d9f02,0xbf584853,0xbf08f59b,0xbf2ac082,0xbf3ebc1b,0xbf63f473,0xbee900b7,0xbf3b8f3b,0xbf2e3bde,0xbf6db293,0xbebe1d4a,
0xbf4ac77f,0xbf1c420c,0xbf756d97,0xbe919ddd,0xbf3504f3,0xbf3504f3,0xbf6c835e,0xbec3ef15,0xbf45e403,0xbf226799,0xbf74fa0b,0xbe94a031,
0xbf54db31,0xbf0e39da,0xbf7b14be,0xbe47c5c2,0xbf61c598,0xbef15aea,0xbf7ec46d,0xbdc8bd36,0xbf4d9f02,0xbf187fc0,0xbf79c79d,0xbe605c13,
0xbf5c61c7,0xbf0242b1,0xbf7e4323,0xbdee3876,0xbf68bf3c,0xbed53641,0xbf7ffb11,0xbc490e90,0xbf7294f8,0xbea395c5,0xbf7eea9d,0x3dbc3ac3,
0xbf61c598,0xbef15aea,0xbf7fb10f,0xbd48fb30,0xbf6db293,0xbebe1d4a,0xbf7f84ab,0x3d7b2b74,0xbf76ba07,0xbe888e93,0xbf7c3b28,0x3e2f10a2,
0xbf7cbfc9,0xbe22abb6,0xbf75dec6,0x3e8e9a22,0xbf710908,0xbeac7cd4,0xbf7e1324,0x3dfab273,0xbf796e4e,0xbe667c66,0xbf78b47b,0x3e72b651,
0xbf7e70b0,0xbde1bc2e,0xbf6ff573,0x3eb263ef,0xbf7ffec4,0x3bc90f88,0xbf63f473,0x3ee900b7,0xbf7b14be,0xbe47c5c2,0xbf74fa0b,0x3e94a031,
0xbf7f4e6d,0xbd96a905,0xbf6a09a7,0x3ecf7bca,0xbf7fb10f,0x3d48fb30,0xbf5b941a,0x3f039c3d,0xbf7c3b28,0x3e2f10a2,0xbf49d112,0x3f1d7fd1,
0xbf7fb10f,0xbd48fb30,0xbf64aa59,0x3ee63375,0xbf7f2f9d,0x3da3308c,0xbf53fac3,0x3f0f8784,0xbf7a7302,0x3e541501,0xbf3fc767,0x3f299415,
0xbf718f57,0x3ea986c4,0xbf286605,0x3f40d0da,0xbf7ec46d,0x3dc8bd36,0xbf4d9f02,0x3f187fc0,0xbf791298,0x3e6c9a7f,0xbf373a23,0x3f32c8c9,
0xbf6ed89e,0x3eb8442a,0xbf1d7fd1,0x3f49d112,0xbf604621,0x3ef6e0cb,0xbf00e7e4,0x3f5d2d53,0xbf7853f8,0x3e78cfcc,0xbf3085bb,0x3f396842,
0xbf6d1c1d,0x3ec1071e,0xbf14b039,0x3f5064af,0xbf5d2d53,0x3f00e7e4,0xbeebcbbb,0x3f633c5a,0xbf48d8b3,0x3f1ebc12,0xbea986c4,0x3f718f57,
0xbf6c835e,0x3ec3ef15,0xbf0e39da,0x3f54db31,0xbf5b941a,0x3f039c3d,0xbedae880,0x3f676bd8,0xbf45e403,0x3f226799,0xbe94a031,0x3f74fa0b,
0xbf2beb4a,0x3f3daef9,0xbe164083,0x3f7d3aac,0xbf5b941a,0x3f039c3d,0xbecf7bca,0x3f6a09a7,0xbf44e3f5,0x3f239da9,0xbe8586ce,0x3f772417,
0xbf299415,0x3f3fc767,0xbde1bc2e,0x3f7e70b0,0xbf0a48ad,0x3f577026,0x3d2fe007,0x3f7fc38f,0xbf45e403,0x3f226799,0xbe78cfcc,0x3f7853f8,
0xbf299415,0x3f3fc767,0xbdafb680,0x3f7f0e58,0xbf08f59b,0x3f584853,0x3d96a905,0x3f7f4e6d,0xbec9b953,0x3f6b4b0c,0x3e6c9a7f,0x3f791298,
0xbf2beb4a,0x3f3daef9,0xbd96a905,0x3f7f4e6d,0xbf0a48ad,0x3f577026,0x3dbc3ac3,0x3f7eea9d,0xbec9b953,0x3f6b4b0c,0x3e827dc0,0x3f778bc5,
0xbe72b651,0x3f78b47b,0x3ed25a09,0x3f696591,0xbf0e39da,0x3f54db31,0x3dc8bd36,0x3f7ec46d,0xbecf7bca,0x3f6a09a7,0x3e888e93,0x3f76ba07,
0xbe78cfcc,0x3f7853f8,0x3edae880,0x3f676bd8,0xbd96a905,0x3f7f4e6d,0x3f13682a,0x3f514d3d,0xbedae880,0x3f676bd8,0x3e888e93,0x3f76ba07,
0xbe8586ce,0x3f772417,0x3eddbe79,0x3f66becc,0xbdafb680,0x3f7f0e58,0x3f15f6d9,0x3f4f7a1f,0x3dbc3ac3,0x3f7eea9d,0x3f385216,0x3f31a81d,
0xbe94a031,0x3f74fa0b,0x3edae880,0x3f676bd8,0xbde1bc2e,0x3f7e70b0,0x3f15f6d9,0x3f4f7a1f,0x3d96a905,0x3f7f4e6d,0x3f396842,0x3f3085bb,
0x3e827dc0,0x3f778bc5,0x3f5695e5,0x3f0b9a6b,0xbe164083,0x3f7d3aac,0x3f13682a,0x3f514d3d,0x3d2fe007,0x3f7fc38f,0x3f385216,0x3f31a81d,
0x3e6c9a7f,0x3f791298,0x3f5695e5,0x3f0b9a6b,0x3ed25a09,0x3f696591,0x3f6d1c1d,0x3ec1071e,
};
__device__ __align__(128) const uint32_t T_TWB[2048] = {
0x3f800000,0x0,0x3f800000,0x0,0x3f800000,0x0,0x3f800000,0x0,0x3f800000,0x0,0x3f800000,0x0,
0x3f800000,0x0,0x3f800000,0x0,0x3f800000,0x0,0x3f7ffec4,0xbbc90f88,0x3f7fec43,0xbcc90ab0,0x3f7fe129,0xbcfb49ba,
0x3f7fb10f,0xbd48fb30,0x3f7f9c18,0xbd621469,0x3f7f4e6d,0xbd96a905,0x3f7f2f9d,0xbda3308c,0x3f800000,0x0,0x3f7ffb11,0xbc490e90,
0x3f7fb10f,0xbd48fb30,0x3f7f84ab,0xbd7b2b74,0x3f7ec46d,0xbdc8bd36,0x3f7e70b0,0xbde1bc2e,0x3f7d3aac,0xbe164083,0x3f7cbfc9,0xbe22abb6,
0x3f800000,0x0,0x3f7ff4e6,0xbc96c9b6,0x3f7f4e6d,0xbd96a905,0x3f7eea9d,0xbdbc3ac3,0x3f7d3aac,0xbe164083,0x3f7c7eb0,0xbe28defc,
0x3f79c79d,0xbe605c13,0x3f78b47b,0xbe72b651,0x3f800000,0x0,0x3f7fec43,0xbcc90ab0,0x3f7ec46d,0xbdc8bd36,0x3f7e1324,0xbdfab273,
0x3f7b14be,0xbe47c5c2,0x3f79c79d,0xbe605c13,0x3f74fa0b,0xbe94a031,0x3f731447,0xbea09ae5,0x3f800000,0x0,0x3f7fe129,0xbcfb49ba,
0x3f7e1324,0xbdfab273,0x3f7cfe73,0xbe1c76de,0x3f7853f8,0xbe78cfcc,0x3f764d97,0xbe8b9507,0x3f6ed89e,0xbeb8442a,0x3f6be858,0xbec6d529,
0x3f800000,0x0,0x3f7fd397,0xbd16c32c,0x3f7d3aac,0xbe164083,0x3f7baccd,0xbe3b6ecf,0x3f74fa0b,0xbe94a031,0x3f721352,0xbea68f12,
0x3f676bd8,0xbedae880,0x3f633c5a,0xbeebcbbb,0x3f800000,0x0,0x3f7fc38f,0xbd2fe007,0x3f7c3b28,0xbe2f10a2,0x3f7a1e84,0xbe5a3997,
0x3f710908,0xbeac7cd4,0x3f6d1c1d,0xbec1071e,0x3f5ebe05,0xbefc5d27,0x3f591e6a,0xbf07a136,0x3f800000,0x0,0x3f7fb10f,0xbd48fb30,
0x3f7b14be,0xbe47c5c2,0x3f7853f8,0xbe78cfcc,0x3f6c835e,0xbec3ef15,0x3f676bd8,0xbedae880,0x3f54db31,0xbf0e39da,0x3f4d9f02,0xbf187fc0,
0x3f800000,0x0,0x3f7f9c18,0xbd621469,0x3f79c79d,0xbe605c13,0x3f764d97,0xbe8b9507,0x3f676bd8,0xbedae880,0x3f6106f2,0xbef41f07,
0x3f49d112,0xbf1d7fd1,0x3f40d0da,0xbf286605,0x3f800000,0x0,0x3f7f84ab,0xbd7b2b74,0x3f7853f8,0xbe78cfcc,0x3f740bdd,0xbe9aa086,
0x3f61c598,0xbef15aea,0x3f59f26a,0xbf064b82,0x3f3daef9,0xbf2beb4a,0x3f32c8c9,0xbf373a23,0x3f800000,0x0,0x3f7f6ac7,0xbd8a200a,
0x3f76ba07,0xbe888e93,0x3f718f57,0xbea986c4,0x3f5b941a,0xbf039c3d,0x3f5233c6,0xbf121eb0,0x3f3085bb,0xbf396842,0x3f239da9,0xbf44e3f5,
0x3f800000,0x0,0x3f7f4e6d,0xbd96a905,0x3f74fa0b,0xbe94a031,0x3f6ed89e,0xbeb8442a,0x3f54db31,0xbf0e39da,0x3f49d112,0xbf1d7fd1,
0x3f226799,0xbf45e403,0x3f13682a,0xbf514d3d,0x3f800000,0x0,0x3f7f2f9d,0xbda3308c,0x3f731447,0xbea09ae5,0x3f6be858,0xbec6d529,
0x3f4d9f02,0xbf187fc0,0x3f40d0da,0xbf286605,0x3f13682a,0xbf514d3d,0x3f0242b1,0xbf5c61c7,0x3f800000,0x0,0x3f7f0e58,0xbdafb680,
0x3f710908,0xbeac7cd4,0x3f68bf3c,0xbed53641,0x3f45e403,0xbf226799,0x3f373a23,0xbf32c8c9,0x3f039c3d,0xbf5b941a,0x3ee0924f,0xbf660f88,
0x3f800000,0x0,0x3f7eea9d,0xbdbc3ac3,0x3f6ed89e,0xbeb8442a,0x3f655e0b,0xbee363fa,0x3f3daef9,0xbf2beb4a,0x3f2d1469,0xbf3ca003,
0x3ee63375,0xbf64aa59,0x3ebb31a0,0xbf6e46be,0x3f800000,0x0,0x3f7ec46d,0xbdc8bd36,0x3f6c835e,0xbec3ef15,0x3f61c598,0xbef15aea,
0x3f3504f3,0xbf3504f3,0x3f226799,0xbf45e403,0x3ec3ef15,0xbf6c835e,0x3e94a031,0xbf74fa0b,0x3f800000,0x0,0x3f7e9bc9,0xbdd53db9,
0x3f6a09a7,0xbecf7bca,0x3f5df6be,0xbeff17b2,0x3f2beb4a,0xbf3daef9,0x3f173c07,0xbf4e8d90,0x3ea09ae5,0xbf731447,0x3e5a3997,0xbf7a1e84,
0x3f800000,0x0,0x3f7e70b0,0xbde1bc2e,0x3f676bd8,0xbedae880,0x3f59f26a,0xbf064b82,0x3f226799,0xbf45e403,0x3f0b9a6b,0xbf5695e5,
0x3e78cfcc,0xbf7853f8,0x3e09cf86,0xbf7dabcc,0x3f800000,0x0,0x3f7e4323,0xbdee3876,0x3f64aa59,0xbee63375,0x3f55b993,0xbf0cead0,
0x3f187fc0,0xbf4d9f02,0x3eff17b2,0xbf5df6be,0x3e2f10a2,0xbf7c3b28,0x3d621469,0xbf7f9c18,0x3f800000,0x0,0x3f7e1324,0xbdfab273,
0x3f61c598,0xbef15aea,0x3f514d3d,0xbf13682a,0x3f0e39da,0xbf54db31,0x3ee63375,0xbf64aa59,0x3dc8bd36,0xbf7ec46d,0xbcc90ab0,0xbf7fec43,
0x3f800000,0x0,0x3f7de0b1,0xbe039502,0x3f5ebe05,0xbefc5d27,0x3f4cae79,0xbf19c200,0x3f039c3d,0xbf5b941a,0x3ecc9b8b,0xbf6aab7b,
0x3cc90ab0,0xbf7fec43,0xbdd53db9,0xbf7e9bc9,0x3f800000,0x0,0x3f7dabcc,0xbe09cf86,0x3f5b941a,0xbf039c3d,0x3f47de65,0xbf1ff6cb,
0x3ef15aea,0xbf61c598,0x3eb263ef,0xbf6ff573,0xbd48fb30,0xbf7fb10f,0xbe3b6ecf,0xbf7baccd,0x3f800000,0x0,0x3f7d7474,0xbe1008b7,
0x3f584853,0xbf08f59b,0x3f42de29,0xbf26050a,0x3edae880,0xbf676bd8,0x3e97a117,0xbf748422,0xbdfab273,0xbf7e1324,0xbe8586ce,0xbf772417,
0x3f800000,0x0,0x3f7d3aac,0xbe164083,0x3f54db31,0xbf0e39da,0x3f3daef9,0xbf2beb4a,0x3ec3ef15,0xbf6c835e,0x3e78cfcc,0xbf7853f8,
0xbe47c5c2,0xbf7b14be,0xbeac7cd4,0xbf710908,0x3f800000,0x0,0x3f7cfe73,0xbe1c76de,0x3f514d3d,0xbf13682a,0x3f385216,0xbf31a81d,
0x3eac7cd4,0xbf710908,0x3e419b37,0xbf7b61fc,0xbe888e93,0xbf76ba07,0xbed25a09,0xbf696591,0x3f800000,0x0,0x3f7cbfc9,0xbe22abb6,
0x3f4d9f02,0xbf187fc0,0x3f32c8c9,0xbf373a23,0x3e94a031,0xbf74fa0b,0x3e09cf86,0xbf7dabcc,0xbeac7cd4,0xbf710908,0xbef6e0cb,0xbf604621,
0x3f800000,0x0,0x3f7c7eb0,0xbe28defc,0x3f49d112,0xbf1d7fd1,0x3f2d1469,0xbf3ca003,0x3e78cfcc,0xbf7853f8,0x3da3308c,0xbf7f2f9d,
0xbecf7bca,0xbf6a09a7,0xbf0cead0,0xbf55b993,0x3f800000,0x0,0x3f7c3b28,0xbe2f10a2,0x3f45e403,0xbf226799,0x3f273656,0xbf41d870,
0x3e47c5c2,0xbf7b14be,0x3cc90ab0,0xbf7fec43,0xbef15aea,0xbf61c598,0xbf1d7fd1,0xbf49d112,0x3f800000,0x0,0x3f7bf531,0xbe354098,
0x3f41d870,0xbf273656,0x3f212ff9,0xbf46e22a,0x3e164083,0xbf7d3aac,0xbcfb49ba,0xbf7fe129,0xbf08f59b,0xbf584853,0xbf2d1469,0xbf3ca003,
0x3f800000,0x0,0x3f7baccd,0xbe3b6ecf,0x3f3daef9,0xbf2beb4a,0x3f1b02c6,0xbf4bbbf8,0x3dc8bd36,0xbf7ec46d,0xbdafb680,0xbf7f0e58,
0xbf187fc0,0xbf4d9f02,0xbf3b8f3b,0xbf2e3bde,0x3f800000,0x0,0x3f7b61fc,0xbe419b37,0x3f396842,0xbf3085bb,0x3f14b039,0xbf5064af,
0x3d48fb30,0xbf7fb10f,0xbe1008b7,0xbf7d7474,0xbf273656,0xbf41d870,0xbf48d8b3,0xbf1ebc12,0x3f800000,0x0,0x3f800000,0x0,
0x3f800000,0x0,0x3f800000,0x0,0x3f800000,0x0,0x3f800000,0x0,0x3f800000,0x0,0x3f800000,0x0,
0x3f7ffb11,0xbc490e90,0x3f7ff4e6,0xbc96c9b6,0x3f7fd397,0xbd16c32c,0x3f7fc38f,0xbd2fe007,0x3f7f84ab,0xbd7b2b74,0x3f7f6ac7,0xbd8a200a,
0x3f7f0e58,0xbdafb680,0x3f7eea9d,0xbdbc3ac3,0x3f7fec43,0xbcc90ab0,0x3f7fd397,0xbd16c32c,0x3f7f4e6d,0xbd96a905,0x3f7f0e58,0xbdafb680,
0x3f7e1324,0xbdfab273,0x3f7dabcc,0xbe09cf86,0x3f7c3b28,0xbe2f10a2,0x3f7baccd,0xbe3b6ecf,0x3f7fd397,0xbd16c32c,0x3f7f9c18,0xbd621469,
0x3f7e70b0,0xbde1bc2e,0x3f7de0b1,0xbe039502,0x3f7baccd,0xbe3b6ecf,0x3f7ac516,0xbe4dee60,0x3f778bc5,0xbe827dc0,0x3f764d97,0xbe8b9507,
0x3f7fb10f,0xbd48fb30,0x3f7f4e6d,0xbd96a905,0x3f7d3aac,0xbe164083,0x3f7c3b28,0xbe2f10a2,0x3f7853f8,0xbe78cfcc,0x3f76ba07,0xbe888e93,
0x3f710908,0xbeac7cd4,0x3f6ed89e,0xbeb8442a,0x3f7f84ab,0xbd7b2b74,0x3f7eea9d,0xbdbc3ac3,0x3f7baccd,0xbe3b6ecf,0x3f7a1e84,0xbe5a3997,
0x3f740bdd,0xbe9aa086,0x3f718f57,0xbea986c4,0x3f68bf3c,0xbed53641,0x3f655e0b,0xbee363fa,0x3f7f4e6d,0xbd96a905,0x3f7e70b0,0xbde1bc2e,
0x3f79c79d,0xbe605c13,0x3f778bc5,0xbe827dc0,0x3f6ed89e,0xbeb8442a,0x3f6b4b0c,0xbec9b953,0x3f5ebe05,0xbefc5d27,0x3f59f26a,0xbf064b82,
0x3f7f0e58,0xbdafb680,0x3f7de0b1,0xbe039502,0x3f778bc5,0xbe827dc0,0x3f748422,0xbe97a117,0x3f68bf3c,0xbed53641,0x3f63f473,0xbee900b7,
0x3f531849,0xbf10d3cd,0x3f4cae79,0xbf19c200,0x3f7ec46d,0xbdc8bd36,0x3f7d3aac,0xbe164083,0x3f74fa0b,0xbe94a031,0x3f710908,0xbeac7cd4,
0x3f61c598,0xbef15aea,0x3f5b941a,0xbf039c3d,0x3f45e403,0xbf226799,0x3f3daef9,0xbf2beb4a,0x3f7e70b0,0xbde1bc2e,0x3f7c7eb0,0xbe28defc,
0x3f721352,0xbea68f12,0x3f6d1c1d,0xbec1071e,0x3f59f26a,0xbf064b82,0x3f5233c6,0xbf121eb0,0x3f373a23,0xbf32c8c9,0x3f2d1469,0xbf3ca003,
0x3f7e1324,0xbdfab273,0x3f7baccd,0xbe3b6ecf,0x3f6ed89e,0xbeb8442a,0x3f68bf3c,0xbed53641,0x3f514d3d,0xbf13682a,0x3f47de65,0xbf1ff6cb,
0x3f273656,0xbf41d870,0x3f1b02c6,0xbf4bbbf8,0x3f7dabcc,0xbe09cf86,0x3f7ac516,0xbe4dee60,0x3f6b4b0c,0xbec9b953,0x3f63f473,0xbee900b7,
0x3f47de65,0xbf1ff6cb,0x3f3ca003,0xbf2d1469,0x3f15f6d9,0xbf4f7a1f,0x3f07a136,0xbf591e6a,0x3f7d3aac,0xbe164083,0x3f79c79d,0xbe605c13,
0x3f676bd8,0xbedae880,0x3f5ebe05,0xbefc5d27,0x3f3daef9,0xbf2beb4a,0x3f3085bb,0xbf396842,0x3f039c3d,0xbf5b941a,0x3ee63375,0xbf64aa59,
0x3f7cbfc9,0xbe22abb6,0x3f78b47b,0xbe72b651,0x3f633c5a,0xbeebcbbb,0x3f591e6a,0xbf07a136,0x3f32c8c9,0xbf373a23,0x3f239da9,0xbf44e3f5,
0x3ee0924f,0xbf660f88,0x3ebb31a0,0xbf6e46be,0x3f7c3b28,0xbe2f10a2,0x3f778bc5,0xbe827dc0,0x3f5ebe05,0xbefc5d27,0x3f531849,0xbf10d3cd,
0x3f273656,0xbf41d870,0x3f15f6d9,0xbf4f7a1f,0x3eb8442a,0xbf6ed89e,0x3e8e9a22,0xbf75dec6,0x3f7baccd,0xbe3b6ecf,0x3f764d97,0xbe8b9507,
0x3f59f26a,0xbf064b82,0x3f4cae79,0xbf19c200,0x3f1b02c6,0xbf4bbbf8,0x3f07a136,0xbf591e6a,0x3e8e9a22,0xbf75dec6,0x3e419b37,0xbf7b61fc,
0x3f7b14be,0xbe47c5c2,0x3f74fa0b,0xbe94a031,0x3f54db31,0xbf0e39da,0x3f45e403,0xbf226799,0x3f0e39da,0xbf54db31,0x3ef15aea,0xbf61c598,
0x3e47c5c2,0xbf7b14be,0x3dc8bd36,0xbf7ec46d,0x3f7a7302,0xbe541501,0x3f73913f,0xbe9d9e78,0x3f4f7a1f,0xbf15f6d9,0x3f3ebc1b,0xbf2ac082,
0x3f00e7e4,0xbf5d2d53,0x3ed25a09,0xbf696591,0x3de1bc2e,0xbf7e70b0,0x3bc90f88,0xbf7ffec4,0x3f79c79d,0xbe605c13,0x3f721352,0xbea68f12,
0x3f49d112,0xbf1d7fd1,0x3f373a23,0xbf32c8c9,0x3ee63375,0xbf64aa59,0x3eb263ef,0xbf6ff573,0x3cc90ab0,0xbf7fec43,0xbdafb680,0xbf7f0e58,
0x3f791298,0xbe6c9a7f,0x3f708066,0xbeaf713a,0x3f43e200,0xbf24d225,0x3f2f61a5,0xbf3a7ca4,0x3ec9b953,0xbf6b4b0c,0x3e919ddd,0xbf756d97,
0xbd7b2b74,0xbf7f84ab,0xbe354098,0xbf7bf531,0x3f7853f8,0xbe78cfcc,0x3f6ed89e,0xbeb8442a,0x3f3daef9,0xbf2beb4a,0x3f273656,0xbf41d870,
0x3eac7cd4,0xbf710908,0x3e605c13,0xbf79c79d,0xbe164083,0xbf7d3aac,0xbe888e93,0xbf76ba07,0x3f778bc5,0xbe827dc0,0x3f6d1c1d,0xbec1071e,
0x3f373a23,0xbf32c8c9,0x3f1ebc12,0xbf48d8b3,0x3e8e9a22,0xbf75dec6,0x3e1c76de,0xbf7cfe73,0xbe6c9a7f,0xbf791298,0xbeb554ec,0xbf6f6830,
0x3f76ba07,0xbe888e93,0x3f6b4b0c,0xbec9b953,0x3f3085bb,0xbf396842,0x3f15f6d9,0xbf4f7a1f,0x3e605c13,0xbf79c79d,0x3dafb680,0xbf7f0e58,
0xbea09ae5,0xbf731447,0xbee0924f,0xbf660f88,0x3f75dec6,0xbe8e9a22,0x3f696591,0xbed25a09,0x3f299415,0xbf3fc767,0x3f0cead0,0xbf55b993,
0x3e22abb6,0xbf7cbfc9,0x3c96c9b6,0xbf7ff4e6,0xbec9b953,0xbf6b4b0c,0xbf04f484,0xbf5ac450,0x3f74fa0b,0xbe94a031,0x3f676bd8,0xbedae880,
0x3f226799,0xbf45e403,0x3f039c3d,0xbf5b941a,0x3dc8bd36,0xbf7ec46d,0xbd48fb30,0xbf7fb10f,0xbef15aea,0xbf61c598,0xbf187fc0,0xbf4d9f02,
0x3f740bdd,0xbe9aa086,0x3f655e0b,0xbee363fa,0x3f1b02c6,0xbf4bbbf8,0x3ef41f07,0xbf6106f2,0x3d16c32c,0xbf7fd397,0xbdee3876,0xbf7e4323,
0xbf0b9a6b,0xbf5695e5,0xbf2ac082,0xbf3ebc1b,0x3f731447,0xbea09ae5,0x3f633c5a,0xbeebcbbb,0x3f13682a,0xbf514d3d,0x3ee0924f,0xbf660f88,
0xbcc90ab0,0xbf7fec43,0xbe3b6ecf,0xbf7baccd,0xbf1d7fd1,0xbf49d112,0xbf3b8f3b,0xbf2e3bde,0x3f721352,0xbea68f12,0x3f6106f2,0xbef41f07,
0x3f0b9a6b,0xbf5695e5,0x3ecc9b8b,0xbf6aab7b,0xbdafb680,0xbf7f0e58,0xbe7ee6e1,0xbf77f110,0xbf2e3bde,0xbf3b8f3b,0xbf4ac77f,0xbf1c420c,
0x3f710908,0xbeac7cd4,0x3f5ebe05,0xbefc5d27,0x3f039c3d,0xbf5b941a,0x3eb8442a,0xbf6ed89e,0xbe164083,0xbf7d3aac,0xbea09ae5,0xbf731447,
0xbf3daef9,0xbf2beb4a,0xbf584853,0xbf08f59b,0x3f6ff573,0xbeb263ef,0x3f5c61c7,0xbf0242b1,0x3ef6e0cb,0xbf604621,0x3ea395c5,0xbf7294f8,
0xbe541501,0xbf7a7302,0xbec1071e,0xbf6d1c1d,0xbf4bbbf8,0xbf1b02c6,0xbf63f473,0xbee900b7,0x3f6ed89e,0xbeb8442a,0x3f59f26a,0xbf064b82,
0x3ee63375,0xbf64aa59,0x3e8e9a22,0xbf75dec6,0xbe888e93,0xbf76ba07,0xbee0924f,0xbf660f88,0xbf584853,0xbf08f59b,0xbf6db293,0xbebe1d4a,
0x3f6db293,0xbebe1d4a,0x3f577026,0xbf0a48ad,0x3ed53641,0xbf68bf3c,0x3e72b651,0xbf78b47b,0xbea68f12,0xbf721352,0xbeff17b2,0xbf5df6be,
0xbf633c5a,0xbeebcbbb,0xbf756d97,0xbe919ddd,0x3f800000,0x0,0x3f800000,0x0,0x3f800000,0x0,0x3f800000,0x0,
0x3f800000,0x0,0x3f800000,0x0,0x3f800000,0x0,0x3f800000,0x0,0x3f7ec46d,0xbdc8bd36,0x3f7e9bc9,0xbdd53db9,
0x3f7e1324,0xbdfab273,0x3f7de0b1,0xbe039502,0x3f7d3aac,0xbe164083,0x3f7cfe73,0xbe1c76de,0x3f7c3b28,0xbe2f10a2,0x3f7bf531,0xbe354098,
0x3f7b14be,0xbe47c5c2,0x3f7a7302,0xbe541501,0x3f7853f8,0xbe78cfcc,0x3f778bc5,0xbe827dc0,0x3f74fa0b,0xbe94a031,0x3f740bdd,0xbe9aa086,
0x3f710908,0xbeac7cd4,0x3f6ff573,0xbeb263ef,0x3f74fa0b,0xbe94a031,0x3f73913f,0xbe9d9e78,0x3f6ed89e,0xbeb8442a,0x3f6d1c1d,0xbec1071e,
0x3f676bd8,0xbedae880,0x3f655e0b,0xbee363fa,0x3f5ebe05,0xbefc5d27,0x3f5c61c7,0xbf0242b1,0x3f6c835e,0xbec3ef15,0x3f6a09a7,0xbecf7bca,
0x3f61c598,0xbef15aea,0x3f5ebe05,0xbefc5d27,0x3f54db31,0xbf0e39da,0x3f514d3d,0xbf13682a,0x3f45e403,0xbf226799,0x3f41d870,0xbf273656,
0x3f61c598,0xbef15aea,0x3f5df6be,0xbeff17b2,0x3f514d3d,0xbf13682a,0x3f4cae79,0xbf19c200,0x3f3daef9,0xbf2beb4a,0x3f385216,0xbf31a81d,
0x3f273656,0xbf41d870,0x3f212ff9,0xbf46e22a,0x3f54db31,0xbf0e39da,0x3f4f7a1f,0xbf15f6d9,0x3f3daef9,0xbf2beb4a,0x3f373a23,0xbf32c8c9,
0x3f226799,0xbf45e403,0x3f1b02c6,0xbf4bbbf8,0x3f039c3d,0xbf5b941a,0x3ef6e0cb,0xbf604621,0x3f45e403,0xbf226799,0x3f3ebc1b,0xbf2ac082,
0x3f273656,0xbf41d870,0x3f1ebc12,0xbf48d8b3,0x3f039c3d,0xbf5b941a,0x3ef41f07,0xbf6106f2,0x3eb8442a,0xbf6ed89e,0x3ea395c5,0xbf7294f8,
0x3f3504f3,0xbf3504f3,0x3f2beb4a,0xbf3daef9,0x3f0e39da,0xbf54db31,0x3f039c3d,0xbf5b941a,0x3ec3ef15,0xbf6c835e,0x3eac7cd4,0xbf710908,
0x3e47c5c2,0xbf7b14be,0x3e164083,0xbf7d3aac,0x3f226799,0xbf45e403,0x3f173c07,0xbf4e8d90,0x3ee63375,0xbf64aa59,0x3ecc9b8b,0xbf6aab7b,
0x3e78cfcc,0xbf7853f8,0x3e419b37,0xbf7b61fc,0x3cc90ab0,0xbf7fec43,0xbcfb49ba,0xbf7fe129,0x3f0e39da,0xbf54db31,0x3f00e7e4,0xbf5d2d53,
0x3eac7cd4,0xbf710908,0x3e8e9a22,0xbf75dec6,0x3dc8bd36,0xbf7ec46d,0x3d16c32c,0xbf7fd397,0xbe164083,0xbf7d3aac,0xbe541501,0xbf7a7302,
0x3ef15aea,0xbf61c598,0x3ed25a09,0xbf696591,0x3e605c13,0xbf79c79d,0x3e1c76de,0xbf7cfe73,0xbd48fb30,0xbf7fb10f,0xbdee3876,0xbf7e4323,
0xbea09ae5,0xbf731447,0xbec1071e,0xbf6d1c1d,0x3ec3ef15,0xbf6c835e,0x3ea09ae5,0xbf731447,0x3dc8bd36,0xbf7ec46d,0x3cc90ab0,0xbf7fec43,
0xbe47c5c2,0xbf7b14be,0xbe888e93,0xbf76ba07,0xbef15aea,0xbf61c598,0xbf08f59b,0xbf584853,0x3e94a031,0xbf74fa0b,0x3e5a3997,0xbf7a1e84,
0xbcc90ab0,0xbf7fec43,0xbdd53db9,0xbf7e9bc9,0xbeac7cd4,0xbf710908,0xbed25a09,0xbf696591,0xbf1d7fd1,0xbf49d112,0xbf2d1469,0xbf3ca003,
0x3e47c5c2,0xbf7b14be,0x3de1bc2e,0xbf7e70b0,0xbe164083,0xbf7d3aac,0xbe6c9a7f,0xbf791298,0xbef15aea,0xbf61c598,0xbf0b9a6b,0xbf5695e5,
0xbf3daef9,0xbf2beb4a,0xbf4bbbf8,0xbf1b02c6,0x3dc8bd36,0xbf7ec46d,0x3bc90f88,0xbf7ffec4,0xbe888e93,0xbf76ba07,0xbeb554ec,0xbf6f6830,
0xbf187fc0,0xbf4d9f02,0xbf2ac082,0xbf3ebc1b,0xbf584853,0xbf08f59b,0xbf63f473,0xbee900b7,0x0,0xbf800000,0xbdc8bd36,0xbf7ec46d,
0xbec3ef15,0xbf6c835e,0xbef15aea,0xbf61c598,0xbf3504f3,0xbf3504f3,0xbf45e403,0xbf226799,0xbf6c835e,0xbec3ef15,0xbf74fa0b,0xbe94a031,
0xbdc8bd36,0xbf7ec46d,0xbe4dee60,0xbf7ac516,0xbefc5d27,0xbf5ebe05,0xbf14b039,0xbf5064af,0xbf4d9f02,0xbf187fc0,0xbf5c61c7,0xbf0242b1,
0xbf79c79d,0xbe605c13,0xbf7e4323,0xbdee3876,0xbe47c5c2,0xbf7b14be,0xbe9aa086,0xbf740bdd,0xbf187fc0,0xbf4d9f02,0xbf2e3bde,0xbf3b8f3b,
0xbf61c598,0xbef15aea,0xbf6db293,0xbebe1d4a,0xbf7fb10f,0xbd48fb30,0xbf7f84ab,0x3d7b2b74,0xbe94a031,0xbf74fa0b,0xbecc9b8b,0xbf6aab7b,
0xbf3085bb,0xbf396842,0xbf44e3f5,0xbf239da9,0xbf710908,0xbeac7cd4,0xbf796e4e,0xbe667c66,0xbf7e1324,0x3dfab273,0xbf78b47b,0x3e72b651,
0xbec3ef15,0xbf6c835e,0xbefc5d27,0xbf5ebe05,0xbf45e403,0xbf226799,0xbf584853,0xbf08f59b,0xbf7b14be,0xbe47c5c2,0xbf7f4e6d,0xbd96a905,
0xbf74fa0b,0x3e94a031,0xbf6a09a7,0x3ecf7bca,0xbef15aea,0xbf61c598,0xbf14b039,0xbf5064af,0xbf584853,0xbf08f59b,0xbf6816a8,0xbed8106b,
0xbf7fb10f,0xbd48fb30,0xbf7f2f9d,0x3da3308c,0xbf64aa59,0x3ee63375,0xbf53fac3,0x3f0f8784,0xbf0e39da,0xbf54db31,0xbf299415,0xbf3fc767,
0xbf676bd8,0xbedae880,0xbf740bdd,0xbe9aa086,0xbf7ec46d,0x3dc8bd36,0xbf791298,0x3e6c9a7f,0xbf4d9f02,0x3f187fc0,0xbf373a23,0x3f32c8c9,
0xbf226799,0xbf45e403,0xbf3ca003,0xbf2d1469,0xbf731447,0xbea09ae5,0xbf7bf531,0xbe354098,0xbf7853f8,0x3e78cfcc,0xbf6d1c1d,0x3ec1071e,
0xbf3085bb,0x3f396842,0xbf14b039,0x3f5064af,0xbf3504f3,0xbf3504f3,0xbf4d9f02,0xbf187fc0,0xbf7b14be,0xbe47c5c2,0xbf7fb10f,0xbd48fb30,
0xbf6c835e,0x3ec3ef15,0xbf5b941a,0x3f039c3d,0xbf0e39da,0x3f54db31,0xbedae880,0x3f676bd8,0xbf45e403,0xbf226799,0xbf5c61c7,0xbf0242b1,
0xbf7f4e6d,0xbd96a905,0xbf7f2f9d,0x3da3308c,0xbf5b941a,0x3f039c3d,0xbf44e3f5,0x3f239da9,0xbecf7bca,0x3f6a09a7,0xbe8586ce,0x3f772417,
0xbf54db31,0xbf0e39da,0xbf68bf3c,0xbed53641,0xbf7fb10f,0x3d48fb30,0xbf7a7302,0x3e541501,0xbf45e403,0x3f226799,0xbf299415,0x3f3fc767,
0xbe78cfcc,0x3f7853f8,0xbdafb680,0x3f7f0e58,0xbf61c598,0xbef15aea,0xbf7294f8,0xbea395c5,0xbf7c3b28,0x3e2f10a2,0xbf718f57,0x3ea986c4,
0xbf2beb4a,0x3f3daef9,0xbf0a48ad,0x3f577026,0xbd96a905,0x3f7f4e6d,0x3dbc3ac3,0x3f7eea9d,0xbf6c835e,0xbec3ef15,0xbf79c79d,0xbe605c13,
0xbf74fa0b,0x3e94a031,0xbf64aa59,0x3ee63375,0xbf0e39da,0x3f54db31,0xbecf7bca,0x3f6a09a7,0x3dc8bd36,0x3f7ec46d,0x3e888e93,0x3f76ba07,
0xbf74fa0b,0xbe94a031,0xbf7e4323,0xbdee3876,0xbf6a09a7,0x3ecf7bca,0xbf53fac3,0x3f0f8784,0xbedae880,0x3f676bd8,0xbe8586ce,0x3f772417,
0x3e888e93,0x3f76ba07,0x3eddbe79,0x3f66becc,0xbf7b14be,0xbe47c5c2,0xbf7ffb11,0xbc490e90,0xbf5b941a,0x3f039c3d,0xbf3fc767,0x3f299415,
0xbe94a031,0x3f74fa0b,0xbde1bc2e,0x3f7e70b0,0x3edae880,0x3f676bd8,0x3f15f6d9,0x3f4f7a1f,0xbf7ec46d,0xbdc8bd36,0xbf7eea9d,0x3dbc3ac3,
0xbf49d112,0x3f1d7fd1,0xbf286605,0x3f40d0da,0xbe164083,0x3f7d3aac,0x3d2fe007,0x3f7fc38f,0x3f13682a,0x3f514d3d,0x3f385216,0x3f31a81d,
0x3f800000,0x0,0x3f800000,0x0,0x3f800000,0x0,0x3f800000,0x0,0x3f800000,0x0,0x3f800000,0x0,
0x3f800000,0x0,0x3f800000,0x0,0x3f7e70b0,0xbde1bc2e,0x3f7e4323,0xbdee3876,0x3f7dabcc,0xbe09cf86,0x3f7d7474,0xbe1008b7,
0x3f7cbfc9,0xbe22abb6,0x3f7c7eb0,0xbe28defc,0x3f7baccd,0xbe3b6ecf,0x3f7b61fc,0xbe419b37,0x3f79c79d,0xbe605c13,0x3f791298,0xbe6c9a7f,
0x3f76ba07,0xbe888e93,0x3f75dec6,0xbe8e9a22,0x3f731447,0xbea09ae5,0x3f721352,0xbea68f12,0x3f6ed89e,0xbeb8442a,0x3f6db293,0xbebe1d4a,
0x3f721352,0xbea68f12,0x3f708066,0xbeaf713a,0x3f6b4b0c,0xbec9b953,0x3f696591,0xbed25a09,0x3f633c5a,0xbeebcbbb,0x3f6106f2,0xbef41f07,
0x3f59f26a,0xbf064b82,0x3f577026,0xbf0a48ad,0x3f676bd8,0xbedae880,0x3f64aa59,0xbee63375,0x3f5b941a,0xbf039c3d,0x3f584853,0xbf08f59b,
0x3f4d9f02,0xbf187fc0,0x3f49d112,0xbf1d7fd1,0x3f3daef9,0xbf2beb4a,0x3f396842,0xbf3085bb,0x3f59f26a,0xbf064b82,0x3f55b993,0xbf0cead0,
0x3f47de65,0xbf1ff6cb,0x3f42de29,0xbf26050a,0x3f32c8c9,0xbf373a23,0x3f2d1469,0xbf3ca003,0x3f1b02c6,0xbf4bbbf8,0x3f14b039,0xbf5064af,
0x3f49d112,0xbf1d7fd1,0x3f43e200,0xbf24d225,0x3f3085bb,0xbf396842,0x3f299415,0xbf3fc767,0x3f13682a,0xbf514d3d,0x3f0b9a6b,0xbf5695e5,
0x3ee63375,0xbf64aa59,0x3ed53641,0xbf68bf3c,0x3f373a23,0xbf32c8c9,0x3f2f61a5,0xbf3a7ca4,0x3f15f6d9,0xbf4f7a1f,0x3f0cead0,0xbf55b993,
0x3ee0924f,0xbf660f88,0x3ecc9b8b,0xbf6aab7b,0x3e8e9a22,0xbf75dec6,0x3e72b651,0xbf78b47b,0x3f226799,0xbf45e403,0x3f187fc0,0xbf4d9f02,
0x3ef15aea,0xbf61c598,0x3edae880,0xbf676bd8,0x3e94a031,0xbf74fa0b,0x3e78cfcc,0xbf7853f8,0x3dc8bd36,0xbf7ec46d,0x3d48fb30,0xbf7fb10f,
0x3f0b9a6b,0xbf5695e5,0x3eff17b2,0xbf5df6be,0x3eb263ef,0xbf6ff573,0x3e97a117,0xbf748422,0x3e09cf86,0xbf7dabcc,0x3da3308c,0xbf7f2f9d,
0xbdafb680,0xbf7f0e58,0xbe1008b7,0xbf7d7474,0x3ee63375,0xbf64aa59,0x3ec9b953,0xbf6b4b0c,0x3e605c13,0xbf79c79d,0x3e22abb6,0xbf7cbfc9,
0xbcc90ab0,0xbf7fec43,0xbdafb680,0xbf7f0e58,0xbe888e93,0xbf76ba07,0xbea68f12,0xbf721352,0x3eb263ef,0xbf6ff573,0x3e919ddd,0xbf756d97,
0x3dafb680,0xbf7f0e58,0x3c96c9b6,0xbf7ff4e6,0xbe3b6ecf,0xbf7baccd,0xbe7ee6e1,0xbf77f110,0xbee0924f,0xbf660f88,0xbeff17b2,0xbf5df6be,
0x3e78cfcc,0xbf7853f8,0x3e2f10a2,0xbf7c3b28,0xbd48fb30,0xbf7fb10f,0xbdfab273,0xbf7e1324,0xbeac7cd4,0xbf710908,0xbecf7bca,0xbf6a09a7,
0xbf187fc0,0xbf4d9f02,0xbf273656,0xbf41d870,0x3e09cf86,0xbf7dabcc,0x3d621469,0xbf7f9c18,0xbe3b6ecf,0xbf7baccd,0xbe8586ce,0xbf772417,
0xbef6e0cb,0xbf604621,0xbf0cead0,0xbf55b993,0xbf3b8f3b,0xbf2e3bde,0xbf48d8b3,0xbf1ebc12,0x3cc90ab0,0xbf7fec43,0xbd7b2b74,0xbf7f84ab,
0xbea09ae5,0xbf731447,0xbec9b953,0xbf6b4b0c,0xbf1d7fd1,0xbf49d112,0xbf2e3bde,0xbf3b8f3b,0xbf584853,0xbf08f59b,0xbf633c5a,0xbeebcbbb,
0xbdafb680,0xbf7f0e58,0xbe354098,0xbf7bf531,0xbee0924f,0xbf660f88,0xbf04f484,0xbf5ac450,0xbf3b8f3b,0xbf2e3bde,0xbf4ac77f,0xbf1c420c,
0xbf6db293,0xbebe1d4a,0xbf756d97,0xbe919ddd,0xbe47c5c2,0xbf7b14be,0xbe94a031,0xbf74fa0b,0xbf0e39da,0xbf54db31,0xbf226799,0xbf45e403,
0xbf54db31,0xbf0e39da,0xbf61c598,0xbef15aea,0xbf7b14be,0xbe47c5c2,0xbf7ec46d,0xbdc8bd36,0xbe9aa086,0xbf740bdd,0xbecc9b8b,0xbf6aab7b,
0xbf299415,0xbf3fc767,0xbf3ca003,0xbf2d1469,0xbf68bf3c,0xbed53641,0xbf7294f8,0xbea395c5,0xbf7ffb11,0xbc490e90,0xbf7eea9d,0x3dbc3ac3,
0xbecf7bca,0xbf6a09a7,0xbf00e7e4,0xbf5d2d53,0xbf41d870,0xbf273656,0xbf531849,0xbf10d3cd,0xbf76ba07,0xbe888e93,0xbf7cbfc9,0xbe22abb6,
0xbf7c3b28,0x3e2f10a2,0xbf75dec6,0x3e8e9a22,0xbf00e7e4,0xbf5d2d53,0xbf19c200,0xbf4cae79,0xbf5695e5,0xbf0b9a6b,0xbf655e0b,0xbee363fa,
0xbf7e70b0,0xbde1bc2e,0xbf7ffec4,0x3bc90f88,0xbf6ff573,0x3eb263ef,0xbf63f473,0x3ee900b7,0xbf187fc0,0xbf4d9f02,0xbf3085bb,0xbf396842,
0xbf676bd8,0xbedae880,0xbf731447,0xbea09ae5,0xbf7fb10f,0x3d48fb30,0xbf7c3b28,0x3e2f10a2,0xbf5b941a,0x3f039c3d,0xbf49d112,0x3f1d7fd1,
0xbf2e3bde,0xbf3b8f3b,0xbf44e3f5,0xbf239da9,0xbf740bdd,0xbe9aa086,0xbf7bf531,0xbe354098,0xbf7a7302,0x3e541501,0xbf718f57,0x3ea986c4,
0xbf3fc767,0x3f299415,0xbf286605,0x3f40d0da,0xbf41d870,0xbf273656,0xbf5695e5,0xbf0b9a6b,0xbf7c3b28,0xbe2f10a2,0xbf7fd397,0xbd16c32c,
0xbf6ed89e,0x3eb8442a,0xbf604621,0x3ef6e0cb,0xbf1d7fd1,0x3f49d112,0xbf00e7e4,0x3f5d2d53,0xbf531849,0xbf10d3cd,0xbf655e0b,0xbee363fa,
0xbf7fd397,0xbd16c32c,0xbf7e9bc9,0x3dd53db9,0xbf5d2d53,0x3f00e7e4,0xbf48d8b3,0x3f1ebc12,0xbeebcbbb,0x3f633c5a,0xbea986c4,0x3f718f57,
0xbf61c598,0xbef15aea,0xbf710908,0xbeac7cd4,0xbf7ec46d,0x3dc8bd36,0xbf7853f8,0x3e78cfcc,0xbf45e403,0x3f226799,0xbf2beb4a,0x3f3daef9,
0xbe94a031,0x3f74fa0b,0xbe164083,0x3f7d3aac,0xbf6db293,0xbebe1d4a,0xbf796e4e,0xbe667c66,0xbf791298,0x3e6c9a7f,0xbf6d1c1d,0x3ec1071e,
0xbf299415,0x3f3fc767,0xbf0a48ad,0x3f577026,0xbde1bc2e,0x3f7e70b0,0x3d2fe007,0x3f7fc38f,0xbf76ba07,0xbe888e93,0xbf7e70b0,0xbde1bc2e,
0xbf6ed89e,0x3eb8442a,0xbf5d2d53,0x3f00e7e4,0xbf08f59b,0x3f584853,0xbec9b953,0x3f6b4b0c,0x3d96a905,0x3f7f4e6d,0x3e6c9a7f,0x3f791298,
0xbf7cbfc9,0xbe22abb6,0xbf7ffec4,0x3bc90f88,0xbf604621,0x3ef6e0cb,0xbf48d8b3,0x3f1ebc12,0xbec9b953,0x3f6b4b0c,0xbe72b651,0x3f78b47b,
0x3e827dc0,0x3f778bc5,0x3ed25a09,0x3f696591,0xbf7fb10f,0xbd48fb30,0xbf7e1324,0x3dfab273,0xbf4d9f02,0x3f187fc0,0xbf3085bb,0x3f396842,
0xbe78cfcc,0x3f7853f8,0xbd96a905,0x3f7f4e6d,0x3edae880,0x3f676bd8,0x3f13682a,0x3f514d3d,0xbf7f84ab,0x3d7b2b74,0xbf78b47b,0x3e72b651,
0xbf373a23,0x3f32c8c9,0xbf14b039,0x3f5064af,0xbdafb680,0x3f7f0e58,0x3dbc3ac3,0x3f7eea9d,0x3f15f6d9,0x3f4f7a1f,0x3f385216,0x3f31a81d,
0xbf7c3b28,0x3e2f10a2,0xbf6ff573,0x3eb263ef,0xbf1d7fd1,0x3f49d112,0xbeebcbbb,0x3f633c5a,0x3d96a905,0x3f7f4e6d,0x3e827dc0,0x3f778bc5,
0x3f396842,0x3f3085bb,0x3f5695e5,0x3f0b9a6b,0xbf75dec6,0x3e8e9a22,0xbf63f473,0x3ee900b7,0xbf00e7e4,0x3f5d2d53,0xbea986c4,0x3f718f57,
0x3e6c9a7f,0x3f791298,0x3ed25a09,0x3f696591,0x3f5695e5,0x3f0b9a6b,0x3f6d1c1d,0x3ec1071e,
};
__device__ __align__(128) const uint32_t T_TH[2048] = {
0x0,0x3f800000,0x3ec3ef15,0x3f6c835e,0x3dc8bd36,0x3f7ec46d,0x3ef15aea,0x3f61c598,0x3e47c5c2,0x3f7b14be,0x3f0e39da,0x3f54db31,
0x3e94a031,0x3f74fa0b,0x3f226799,0x3f45e403,0x3b490fc6,0x3f7fffb1,0x3ec5625c,0x3f6c3624,0x3dcefdb7,0x3f7eb069,0x3ef2bd43,0x3f61668a,
0x3e4ada4f,0x3f7aed37,0x3f0ee0db,0x3f546b3b,0x3e9620d2,0x3f74bf62,0x3f2302d3,0x3f456439,0x3bc90f88,0x3f7ffec4,0x3ec6d529,0x3f6be858,
0x3dd53db9,0x3f7e9bc9,0x3ef41f07,0x3f6106f2,0x3e4dee60,0x3f7ac516,0x3f0f8784,0x3f53fac3,0x3e97a117,0x3f748422,0x3f239da9,0x3f44e3f5,
0x3c16cb58,0x3f7ffd39,0x3ec8477c,0x3f6b99fb,0x3ddb7d37,0x3f7e868b,0x3ef58035,0x3f60a6cf,0x3e5101f1,0x3f7a9c59,0x3f102dd5,0x3f5389c7,
0x3e9920fe,0x3f74484b,0x3f24381a,0x3f446337,0x3c490e90,0x3f7ffb11,0x3ec9b953,0x3f6b4b0c,0x3de1bc2e,0x3f7e70b0,0x3ef6e0cb,0x3f604621,
0x3e541501,0x3f7a7302,0x3f10d3cd,0x3f531849,0x3e9aa086,0x3f740bdd,0x3f24d225,0x3f43e200,0x3c7b514b,0x3f7ff84a,0x3ecb2aae,0x3f6afb8c,
0x3de7fa9a,0x3f7e5a38,0x3ef840c8,0x3f5fe4e9,0x3e57278f,0x3f7a4910,0x3f11796b,0x3f52a649,0x3e9c1faf,0x3f73ced9,0x3f256bcb,0x3f436051,
0x3c96c9b6,0x3f7ff4e6,0x3ecc9b8b,0x3f6aab7b,0x3dee3876,0x3f7e4323,0x3ef9a02d,0x3f5f8327,0x3e5a3997,0x3f7a1e84,0x3f121eb0,0x3f5233c6,
0x3e9d9e78,0x3f73913f,0x3f26050a,0x3f42de29,0x3cafea69,0x3f7ff0e3,0x3ece0bea,0x3f6a5ad9,0x3df475c0,0x3f7e2b72,0x3efafef7,0x3f5f20db,
0x3e5d4b1a,0x3f79f35e,0x3f12c39a,0x3f51c0c2,0x3e9f1cdf,0x3f73530e,0x3f269de3,0x3f425b89,0x3cc90ab0,0x3f7fec43,0x3ecf7bca,0x3f6a09a7,
0x3dfab273,0x3f7e1324,0x3efc5d27,0x3f5ebe05,0x3e605c13,0x3f79c79d,0x3f13682a,0x3f514d3d,0x3ea09ae5,0x3f731447,0x3f273656,0x3f41d870,
0x3ce22a7a,0x3f7fe705,0x3ed0eb2a,0x3f69b7e4,0x3e007745,0x3f7dfa38,0x3efdbabb,0x3f5e5aa6,0x3e636c83,0x3f799b43,0x3f140c5f,0x3f50d937,
0x3ea21887,0x3f72d4eb,0x3f27ce61,0x3f4154e1,0x3cfb49ba,0x3f7fe129,0x3ed25a09,0x3f696591,0x3e039502,0x3f7de0b1,0x3eff17b2,0x3f5df6be,
0x3e667c66,0x3f796e4e,0x3f14b039,0x3f5064af,0x3ea395c5,0x3f7294f8,0x3f286605,0x3f40d0da,0x3d0a342f,0x3f7fdaaf,0x3ed3c867,0x3f6912ae,
0x3e06b26e,0x3f7dc68c,0x3f003a06,0x3f5d924d,0x3e698bba,0x3f7940c0,0x3f1553b7,0x3f4fefa8,0x3ea5129f,0x3f725470,0x3f28fd41,0x3f404c5c,
0x3d16c32c,0x3f7fd397,0x3ed53641,0x3f68bf3c,0x3e09cf86,0x3f7dabcc,0x3f00e7e4,0x3f5d2d53,0x3e6c9a7f,0x3f791298,0x3f15f6d9,0x3f4f7a1f,
0x3ea68f12,0x3f721352,0x3f299415,0x3f3fc767,0x3d2351cb,0x3f7fcbe2,0x3ed6a399,0x3f686b39,0x3e0cec4a,0x3f7d906e,0x3f019573,0x3f5cc7d1,
0x3e6fa8b2,0x3f78e3d6,0x3f16999f,0x3f4f0417,0x3ea80b1f,0x3f71d19f,0x3f2a2a80,0x3f3f41fc,0x3d2fe007,0x3f7fc38f,0x3ed8106b,0x3f6816a8,
0x3e1008b7,0x3f7d7474,0x3f0242b1,0x3f5c61c7,0x3e72b651,0x3f78b47b,0x3f173c07,0x3f4e8d90,0x3ea986c4,0x3f718f57,0x3f2ac082,0x3f3ebc1b,
0x3d3c6dd5,0x3f7fba9e,0x3ed97cb9,0x3f67c187,0x3e1324ca,0x3f7d57de,0x3f02ef9f,0x3f5bfb34,0x3e75c35a,0x3f788486,0x3f17de12,0x3f4e1689,
0x3eab0201,0x3f714c7a,0x3f2b561b,0x3f3e35c5,0x3d48fb30,0x3f7fb10f,0x3edae880,0x3f676bd8,0x3e164083,0x3f7d3aac,0x3f039c3d,0x3f5b941a,
0x3e78cfcc,0x3f7853f8,0x3f187fc0,0x3f4d9f02,0x3eac7cd4,0x3f710908,0x3f2beb4a,0x3f3daef9,0x3d55880e,0x3f7fa6e3,0x3edc53c1,0x3f671599,
0x3e195be0,0x3f7d1cdd,0x3f044889,0x3f5b2c79,0x3e7bdba4,0x3f7822d1,0x3f19210f,0x3f4d26fd,0x3eadf73c,0x3f70c501,0x3f2c800f,0x3f3d27b8,
0x3d621469,0x3f7f9c18,0x3eddbe79,0x3f66becc,0x3e1c76de,0x3f7cfe73,0x3f04f484,0x3f5ac450,0x3e7ee6e1,0x3f77f110,0x3f19c200,0x3f4cae79,
0x3eaf713a,0x3f708066,0x3f2d1469,0x3f3ca003,0x3d6ea038,0x3f7f90b1,0x3edf28a9,0x3f666771,0x3e1f917b,0x3f7cdf6c,0x3f05a02c,0x3f5a5ba0,
0x3e80f8c0,0x3f77beb7,0x3f1a6293,0x3f4c3578,0x3eb0eacb,0x3f703b37,0x3f2da859,0x3f3c17d9,0x3d7b2b74,0x3f7f84ab,0x3ee0924f,0x3f660f88,
0x3e22abb6,0x3f7cbfc9,0x3f064b82,0x3f59f26a,0x3e827dc0,0x3f778bc5,0x3f1b02c6,0x3f4bbbf8,0x3eb263ef,0x3f6ff573,0x3f2e3bde,0x3f3b8f3b,
0x3d83db0a,0x3f7f7808,0x3ee1fb6a,0x3f65b710,0x3e25c58c,0x3f7c9f8a,0x3f06f686,0x3f5988ad,0x3e840270,0x3f77583a,0x3f1ba299,0x3f4b41fa,
0x3eb3dca5,0x3f6faf1b,0x3f2ecef7,0x3f3b0629,0x3d8a200a,0x3f7f6ac7,0x3ee363fa,0x3f655e0b,0x3e28defc,0x3f7c7eb0,0x3f07a136,0x3f591e6a,
0x3e8586ce,0x3f772417,0x3f1c420c,0x3f4ac77f,0x3eb554ec,0x3f6f6830,0x3f2f61a5,0x3f3a7ca4,0x3d9064b4,0x3f7f5ce9,0x3ee4cbfe,0x3f650479,
0x3e2bf804,0x3f7c5d3a,0x3f084b92,0x3f58b3a1,0x3e870ada,0x3f76ef5b,0x3f1ce11f,0x3f4a4c87,0x3eb6ccc3,0x3f6f20b0,0x3f2ff3e6,0x3f39f2ac,
0x3d96a905,0x3f7f4e6d,0x3ee63375,0x3f64aa59,0x3e2f10a2,0x3f7c3b28,0x3f08f59b,0x3f584853,0x3e888e93,0x3f76ba07,0x3f1d7fd1,0x3f49d112,
0x3eb8442a,0x3f6ed89e,0x3f3085bb,0x3f396842,0x3d9cecf9,0x3f7f3f54,0x3ee79a5d,0x3f644fac,0x3e3228d4,0x3f7c187a,0x3f099f4e,0x3f57dc7f,
0x3e8a11f7,0x3f76841b,0x3f1e1e22,0x3f495521,0x3eb9bb1e,0x3f6e8ff8,0x3f311722,0x3f38dd65,0x3da3308c,0x3f7f2f9d,0x3ee900b7,0x3f63f473,
0x3e354098,0x3f7bf531,0x3f0a48ad,0x3f577026,0x3e8b9507,0x3f764d97,0x3f1ebc12,0x3f48d8b3,0x3ebb31a0,0x3f6e46be,0x3f31a81d,0x3f385216,
0x3da973ba,0x3f7f1f49,0x3eea6681,0x3f6398ac,0x3e3857ec,0x3f7bd14d,0x3f0af1b7,0x3f570348,0x3e8d17c0,0x3f76167a,0x3f1f599f,0x3f485bca,
0x3ebca7af,0x3f6dfcf2,0x3f3238aa,0x3f37c655,0x3dafb680,0x3f7f0e58,0x3eebcbbb,0x3f633c5a,0x3e3b6ecf,0x3f7baccd,0x3f0b9a6b,0x3f5695e5,
0x3e8e9a22,0x3f75dec6,0x3f1ff6cb,0x3f47de65,0x3ebe1d4a,0x3f6db293,0x3f32c8c9,0x3f373a23,0x3db5f8da,0x3f7efcc9,0x3eed3063,0x3f62df7b,
0x3e3e853e,0x3f7b87b2,0x3f0c42c9,0x3f5627fe,0x3e901c2c,0x3f75a67b,0x3f209393,0x3f476085,0x3ebf926f,0x3f6d67a1,0x3f33587a,0x3f36ad7f,
0x3dbc3ac3,0x3f7eea9d,0x3eee9479,0x3f628210,0x3e419b37,0x3f7b61fc,0x3f0cead0,0x3f55b993,0x3e919ddd,0x3f756d97,0x3f212ff9,0x3f46e22a,
0x3ec1071e,0x3f6d1c1d,0x3f33e7bc,0x3f36206c,0x3dc27c39,0x3f7ed7d4,0x3eeff7fb,0x3f62241a,0x3e44b0b9,0x3f7b3bab,0x3f0d9281,0x3f554aa4,
0x3e931f35,0x3f75341d,0x3f21cbfb,0x3f466354,0x3ec27b55,0x3f6cd007,0x3f34768f,0x3f3592e7,0x3f3504f3,0x3f3504f3,0x3f6c835e,0x3ec3ef15,
0x3f45e403,0x3f226799,0x3f74fa0b,0x3e94a031,0x3f54db31,0x3f0e39da,0x3f7b14be,0x3e47c5c2,0x3f61c598,0x3ef15aea,0x3f7ec46d,0x3dc8bd36,
0x3f3592e7,0x3f34768f,0x3f6cd007,0x3ec27b55,0x3f466354,0x3f21cbfb,0x3f75341d,0x3e931f35,0x3f554aa4,0x3f0d9281,0x3f7b3bab,0x3e44b0b9,
0x3f62241a,0x3eeff7fb,0x3f7ed7d4,0x3dc27c39,0x3f36206c,0x3f33e7bc,0x3f6d1c1d,0x3ec1071e,0x3f46e22a,0x3f212ff9,0x3f756d97,0x3e919ddd,
0x3f55b993,0x3f0cead0,0x3f7b61fc,0x3e419b37,0x3f628210,0x3eee9479,0x3f7eea9d,0x3dbc3ac3,0x3f36ad7f,0x3f33587a,0x3f6d67a1,0x3ebf926f,
0x3f476085,0x3f209393,0x3f75a67b,0x3e901c2c,0x3f5627fe,0x3f0c42c9,0x3f7b87b2,0x3e3e853e,0x3f62df7b,0x3eed3063,0x3f7efcc9,0x3db5f8da,
0x3f373a23,0x3f32c8c9,0x3f6db293,0x3ebe1d4a,0x3f47de65,0x3f1ff6cb,0x3f75dec6,0x3e8e9a22,0x3f5695e5,0x3f0b9a6b,0x3f7baccd,0x3e3b6ecf,
0x3f633c5a,0x3eebcbbb,0x3f7f0e58,0x3dafb680,0x3f37c655,0x3f3238aa,0x3f6dfcf2,0x3ebca7af,0x3f485bca,0x3f1f599f,0x3f76167a,0x3e8d17c0,
0x3f570348,0x3f0af1b7,0x3f7bd14d,0x3e3857ec,0x3f6398ac,0x3eea6681,0x3f7f1f49,0x3da973ba,0x3f385216,0x3f31a81d,0x3f6e46be,0x3ebb31a0,
0x3f48d8b3,0x3f1ebc12,0x3f764d97,0x3e8b9507,0x3f577026,0x3f0a48ad,0x3f7bf531,0x3e354098,0x3f63f473,0x3ee900b7,0x3f7f2f9d,0x3da3308c,
0x3f38dd65,0x3f311722,0x3f6e8ff8,0x3eb9bb1e,0x3f495521,0x3f1e1e22,0x3f76841b,0x3e8a11f7,0x3f57dc7f,0x3f099f4e,0x3f7c187a,0x3e3228d4,
0x3f644fac,0x3ee79a5d,0x3f7f3f54,0x3d9cecf9,0x3f396842,0x3f3085bb,0x3f6ed89e,0x3eb8442a,0x3f49d112,0x3f1d7fd1,0x3f76ba07,0x3e888e93,
0x3f584853,0x3f08f59b,0x3f7c3b28,0x3e2f10a2,0x3f64aa59,0x3ee63375,0x3f7f4e6d,0x3d96a905,0x3f39f2ac,0x3f2ff3e6,0x3f6f20b0,0x3eb6ccc3,
0x3f4a4c87,0x3f1ce11f,0x3f76ef5b,0x3e870ada,0x3f58b3a1,0x3f084b92,0x3f7c5d3a,0x3e2bf804,0x3f650479,0x3ee4cbfe,0x3f7f5ce9,0x3d9064b4,
0x3f3a7ca4,0x3f2f61a5,0x3f6f6830,0x3eb554ec,0x3f4ac77f,0x3f1c420c,0x3f772417,0x3e8586ce,0x3f591e6a,0x3f07a136,0x3f7c7eb0,0x3e28defc,
0x3f655e0b,0x3ee363fa,0x3f7f6ac7,0x3d8a200a,0x3f3b0629,0x3f2ecef7,0x3f6faf1b,0x3eb3dca5,0x3f4b41fa,0x3f1ba299,0x3f77583a,0x3e840270,
0x3f5988ad,0x3f06f686,0x3f7c9f8a,0x3e25c58c,0x3f65b710,0x3ee1fb6a,0x3f7f7808,0x3d83db0a,0x3f3b8f3b,0x3f2e3bde,0x3f6ff573,0x3eb263ef,
0x3f4bbbf8,0x3f1b02c6,0x3f778bc5,0x3e827dc0,0x3f59f26a,0x3f064b82,0x3f7cbfc9,0x3e22abb6,0x3f660f88,0x3ee0924f,0x3f7f84ab,0x3d7b2b74,
0x3f3c17d9,0x3f2da859,0x3f703b37,0x3eb0eacb,0x3f4c3578,0x3f1a6293,0x3f77beb7,0x3e80f8c0,0x3f5a5ba0,0x3f05a02c,0x3f7cdf6c,0x3e1f917b,
0x3f666771,0x3edf28a9,0x3f7f90b1,0x3d6ea038,0x3f3ca003,0x3f2d1469,0x3f708066,0x3eaf713a,0x3f4cae79,0x3f19c200,0x3f77f110,0x3e7ee6e1,
0x3f5ac450,0x3f04f484,0x3f7cfe73,0x3e1c76de,0x3f66becc,0x3eddbe79,0x3f7f9c18,0x3d621469,0x3f3d27b8,0x3f2c800f,0x3f70c501,0x3eadf73c,
0x3f4d26fd,0x3f19210f,0x3f7822d1,0x3e7bdba4,0x3f5b2c79,0x3f044889,0x3f7d1cdd,0x3e195be0,0x3f671599,0x3edc53c1,0x3f7fa6e3,0x3d55880e,
0x3f3daef9,0x3f2beb4a,0x3f710908,0x3eac7cd4,0x3f4d9f02,0x3f187fc0,0x3f7853f8,0x3e78cfcc,0x3f5b941a,0x3f039c3d,0x3f7d3aac,0x3e164083,
0x3f676bd8,0x3edae880,0x3f7fb10f,0x3d48fb30,0x3f3e35c5,0x3f2b561b,0x3f714c7a,0x3eab0201,0x3f4e1689,0x3f17de12,0x3f788486,0x3e75c35a,
0x3f5bfb34,0x3f02ef9f,0x3f7d57de,0x3e1324ca,0x3f67c187,0x3ed97cb9,0x3f7fba9e,0x3d3c6dd5,0x3f3ebc1b,0x3f2ac082,0x3f718f57,0x3ea986c4,
0x3f4e8d90,0x3f173c07,0x3f78b47b,0x3e72b651,0x3f5c61c7,0x3f0242b1,0x3f7d7474,0x3e1008b7,0x3f6816a8,0x3ed8106b,0x3f7fc38f,0x3d2fe007,
0x3f3f41fc,0x3f2a2a80,0x3f71d19f,0x3ea80b1f,0x3f4f0417,0x3f16999f,0x3f78e3d6,0x3e6fa8b2,0x3f5cc7d1,0x3f019573,0x3f7d906e,0x3e0cec4a,
0x3f686b39,0x3ed6a399,0x3f7fcbe2,0x3d2351cb,0x3f3fc767,0x3f299415,0x3f721352,0x3ea68f12,0x3f4f7a1f,0x3f15f6d9,0x3f791298,0x3e6c9a7f,
0x3f5d2d53,0x3f00e7e4,0x3f7dabcc,0x3e09cf86,0x3f68bf3c,0x3ed53641,0x3f7fd397,0x3d16c32c,0x3f404c5c,0x3f28fd41,0x3f725470,0x3ea5129f,
0x3f4fefa8,0x3f1553b7,0x3f7940c0,0x3e698bba,0x3f5d924d,0x3f003a06,0x3f7dc68c,0x3e06b26e,0x3f6912ae,0x3ed3c867,0x3f7fdaaf,0x3d0a342f,
0x3f40d0da,0x3f286605,0x3f7294f8,0x3ea395c5,0x3f5064af,0x3f14b039,0x3f796e4e,0x3e667c66,0x3f5df6be,0x3eff17b2,0x3f7de0b1,0x3e039502,
0x3f696591,0x3ed25a09,0x3f7fe129,0x3cfb49ba,0x3f4154e1,0x3f27ce61,0x3f72d4eb,0x3ea21887,0x3f50d937,0x3f140c5f,0x3f799b43,0x3e636c83,
0x3f5e5aa6,0x3efdbabb,0x3f7dfa38,0x3e007745,0x3f69b7e4,0x3ed0eb2a,0x3f7fe705,0x3ce22a7a,0x3f41d870,0x3f273656,0x3f731447,0x3ea09ae5,
0x3f514d3d,0x3f13682a,0x3f79c79d,0x3e605c13,0x3f5ebe05,0x3efc5d27,0x3f7e1324,0x3dfab273,0x3f6a09a7,0x3ecf7bca,0x3f7fec43,0x3cc90ab0,
0x3f425b89,0x3f269de3,0x3f73530e,0x3e9f1cdf,0x3f51c0c2,0x3f12c39a,0x3f79f35e,0x3e5d4b1a,0x3f5f20db,0x3efafef7,0x3f7e2b72,0x3df475c0,
0x3f6a5ad9,0x3ece0bea,0x3f7ff0e3,0x3cafea69,0x3f42de29,0x3f26050a,0x3f73913f,0x3e9d9e78,0x3f5233c6,0x3f121eb0,0x3f7a1e84,0x3e5a3997,
0x3f5f8327,0x3ef9a02d,0x3f7e4323,0x3dee3876,0x3f6aab7b,0x3ecc9b8b,0x3f7ff4e6,0x3c96c9b6,0x3f436051,0x3f256bcb,0x3f73ced9,0x3e9c1faf,
0x3f52a649,0x3f11796b,0x3f7a4910,0x3e57278f,0x3f5fe4e9,0x3ef840c8,0x3f7e5a38,0x3de7fa9a,0x3f6afb8c,0x3ecb2aae,0x3f7ff84a,0x3c7b514b,
0x3f43e200,0x3f24d225,0x3f740bdd,0x3e9aa086,0x3f531849,0x3f10d3cd,0x3f7a7302,0x3e541501,0x3f604621,0x3ef6e0cb,0x3f7e70b0,0x3de1bc2e,
0x3f6b4b0c,0x3ec9b953,0x3f7ffb11,0x3c490e90,0x3f446337,0x3f24381a,0x3f74484b,0x3e9920fe,0x3f5389c7,0x3f102dd5,0x3f7a9c59,0x3e5101f1,
0x3f60a6cf,0x3ef58035,0x3f7e868b,0x3ddb7d37,0x3f6b99fb,0x3ec8477c,0x3f7ffd39,0x3c16cb58,0x3f44e3f5,0x3f239da9,0x3f748422,0x3e97a117,
0x3f53fac3,0x3f0f8784,0x3f7ac516,0x3e4dee60,0x3f6106f2,0x3ef41f07,0x3f7e9bc9,0x3dd53db9,0x3f6be858,0x3ec6d529,0x3f7ffec4,0x3bc90f88,
0x3f456439,0x3f2302d3,0x3f74bf62,0x3e9620d2,0x3f546b3b,0x3f0ee0db,0x3f7aed37,0x3e4ada4f,0x3f61668a,0x3ef2bd43,0x3f7eb069,0x3dcefdb7,
0x3f6c3624,0x3ec5625c,0x3f7fffb1,0x3b490fc6,0x3f800000,0x248d3132,0x3f6c835e,0xbec3ef15,0x3f7ec46d,0xbdc8bd36,0x3f61c598,0xbef15aea,
0x3f7b14be,0xbe47c5c2,0x3f54db31,0xbf0e39da,0x3f74fa0b,0xbe94a031,0x3f45e403,0xbf226799,0x3f7fffb1,0xbb490fc6,0x3f6c3624,0xbec5625c,
0x3f7eb069,0xbdcefdb7,0x3f61668a,0xbef2bd43,0x3f7aed37,0xbe4ada4f,0x3f546b3b,0xbf0ee0db,0x3f74bf62,0xbe9620d2,0x3f456439,0xbf2302d3,
0x3f7ffec4,0xbbc90f88,0x3f6be858,0xbec6d529,0x3f7e9bc9,0xbdd53db9,0x3f6106f2,0xbef41f07,0x3f7ac516,0xbe4dee60,0x3f53fac3,0xbf0f8784,
0x3f748422,0xbe97a117,0x3f44e3f5,0xbf239da9,0x3f7ffd39,0xbc16cb58,0x3f6b99fb,0xbec8477c,0x3f7e868b,0xbddb7d37,0x3f60a6cf,0xbef58035,
0x3f7a9c59,0xbe5101f1,0x3f5389c7,0xbf102dd5,0x3f74484b,0xbe9920fe,0x3f446337,0xbf24381a,0x3f7ffb11,0xbc490e90,0x3f6b4b0c,0xbec9b953,
0x3f7e70b0,0xbde1bc2e,0x3f604621,0xbef6e0cb,0x3f7a7302,0xbe541501,0x3f531849,0xbf10d3cd,0x3f740bdd,0xbe9aa086,0x3f43e200,0xbf24d225,
0x3f7ff84a,0xbc7b514b,0x3f6afb8c,0xbecb2aae,0x3f7e5a38,0xbde7fa9a,0x3f5fe4e9,0xbef840c8,0x3f7a4910,0xbe57278f,0x3f52a649,0xbf11796b,
0x3f73ced9,0xbe9c1faf,0x3f436051,0xbf256bcb,0x3f7ff4e6,0xbc96c9b6,0x3f6aab7b,0xbecc9b8b,0x3f7e4323,0xbdee3876,0x3f5f8327,0xbef9a02d,
0x3f7a1e84,0xbe5a3997,0x3f5233c6,0xbf121eb0,0x3f73913f,0xbe9d9e78,0x3f42de29,0xbf26050a,0x3f7ff0e3,0xbcafea69,0x3f6a5ad9,0xbece0bea,
0x3f7e2b72,0xbdf475c0,0x3f5f20db,0xbefafef7,0x3f79f35e,0xbe5d4b1a,0x3f51c0c2,0xbf12c39a,0x3f73530e,0xbe9f1cdf,0x3f425b89,0xbf269de3,
0x3f7fec43,0xbcc90ab0,0x3f6a09a7,0xbecf7bca,0x3f7e1324,0xbdfab273,0x3f5ebe05,0xbefc5d27,0x3f79c79d,0xbe605c13,0x3f514d3d,0xbf13682a,
0x3f731447,0xbea09ae5,0x3f41d870,0xbf273656,0x3f7fe705,0xbce22a7a,0x3f69b7e4,0xbed0eb2a,0x3f7dfa38,0xbe007745,0x3f5e5aa6,0xbefdbabb,
0x3f799b43,0xbe636c83,0x3f50d937,0xbf140c5f,0x3f72d4eb,0xbea21887,0x3f4154e1,0xbf27ce61,0x3f7fe129,0xbcfb49ba,0x3f696591,0xbed25a09,
0x3f7de0b1,0xbe039502,0x3f5df6be,0xbeff17b2,0x3f796e4e,0xbe667c66,0x3f5064af,0xbf14b039,0x3f7294f8,0xbea395c5,0x3f40d0da,0xbf286605,
0x3f7fdaaf,0xbd0a342f,0x3f6912ae,0xbed3c867,0x3f7dc68c,0xbe06b26e,0x3f5d924d,0xbf003a06,0x3f7940c0,0xbe698bba,0x3f4fefa8,0xbf1553b7,
0x3f725470,0xbea5129f,0x3f404c5c,0xbf28fd41,0x3f7fd397,0xbd16c32c,0x3f68bf3c,0xbed53641,0x3f7dabcc,0xbe09cf86,0x3f5d2d53,0xbf00e7e4,
0x3f791298,0xbe6c9a7f,0x3f4f7a1f,0xbf15f6d9,0x3f721352,0xbea68f12,0x3f3fc767,0xbf299415,0x3f7fcbe2,0xbd2351cb,0x3f686b39,0xbed6a399,
0x3f7d906e,0xbe0cec4a,0x3f5cc7d1,0xbf019573,0x3f78e3d6,0xbe6fa8b2,0x3f4f0417,0xbf16999f,0x3f71d19f,0xbea80b1f,0x3f3f41fc,0xbf2a2a80,
0x3f7fc38f,0xbd2fe007,0x3f6816a8,0xbed8106b,0x3f7d7474,0xbe1008b7,0x3f5c61c7,0xbf0242b1,0x3f78b47b,0xbe72b651,0x3f4e8d90,0xbf173c07,
0x3f718f57,0xbea986c4,0x3f3ebc1b,0xbf2ac082,0x3f7fba9e,0xbd3c6dd5,0x3f67c187,0xbed97cb9,0x3f7d57de,0xbe1324ca,0x3f5bfb34,0xbf02ef9f,
0x3f788486,0xbe75c35a,0x3f4e1689,0xbf17de12,0x3f714c7a,0xbeab0201,0x3f3e35c5,0xbf2b561b,0x3f7fb10f,0xbd48fb30,0x3f676bd8,0xbedae880,
0x3f7d3aac,0xbe164083,0x3f5b941a,0xbf039c3d,0x3f7853f8,0xbe78cfcc,0x3f4d9f02,0xbf187fc0,0x3f710908,0xbeac7cd4,0x3f3daef9,0xbf2beb4a,
0x3f7fa6e3,0xbd55880e,0x3f671599,0xbedc53c1,0x3f7d1cdd,0xbe195be0,0x3f5b2c79,0xbf044889,0x3f7822d1,0xbe7bdba4,0x3f4d26fd,0xbf19210f,
0x3f70c501,0xbeadf73c,0x3f3d27b8,0xbf2c800f,0x3f7f9c18,0xbd621469,0x3f66becc,0xbeddbe79,0x3f7cfe73,0xbe1c76de,0x3f5ac450,0xbf04f484,
0x3f77f110,0xbe7ee6e1,0x3f4cae79,0xbf19c200,0x3f708066,0xbeaf713a,0x3f3ca003,0xbf2d1469,0x3f7f90b1,0xbd6ea038,0x3f666771,0xbedf28a9,
0x3f7cdf6c,0xbe1f917b,0x3f5a5ba0,0xbf05a02c,0x3f77beb7,0xbe80f8c0,0x3f4c3578,0xbf1a6293,0x3f703b37,0xbeb0eacb,0x3f3c17d9,0xbf2da859,
0x3f7f84ab,0xbd7b2b74,0x3f660f88,0xbee0924f,0x3f7cbfc9,0xbe22abb6,0x3f59f26a,0xbf064b82,0x3f778bc5,0xbe827dc0,0x3f4bbbf8,0xbf1b02c6,
0x3f6ff573,0xbeb263ef,0x3f3b8f3b,0xbf2e3bde,0x3f7f7808,0xbd83db0a,0x3f65b710,0xbee1fb6a,0x3f7c9f8a,0xbe25c58c,0x3f5988ad,0xbf06f686,
0x3f77583a,0xbe840270,0x3f4b41fa,0xbf1ba299,0x3f6faf1b,0xbeb3dca5,0x3f3b0629,0xbf2ecef7,0x3f7f6ac7,0xbd8a200a,0x3f655e0b,0xbee363fa,
0x3f7c7eb0,0xbe28defc,0x3f591e6a,0xbf07a136,0x3f772417,0xbe8586ce,0x3f4ac77f,0xbf1c420c,0x3f6f6830,0xbeb554ec,0x3f3a7ca4,0xbf2f61a5,
0x3f7f5ce9,0xbd9064b4,0x3f650479,0xbee4cbfe,0x3f7c5d3a,0xbe2bf804,0x3f58b3a1,0xbf084b92,0x3f76ef5b,0xbe870ada,0x3f4a4c87,0xbf1ce11f,
0x3f6f20b0,0xbeb6ccc3,0x3f39f2ac,0xbf2ff3e6,0x3f7f4e6d,0xbd96a905,0x3f64aa59,0xbee63375,0x3f7c3b28,0xbe2f10a2,0x3f584853,0xbf08f59b,
0x3f76ba07,0xbe888e93,0x3f49d112,0xbf1d7fd1,0x3f6ed89e,0xbeb8442a,0x3f396842,0xbf3085bb,0x3f7f3f54,0xbd9cecf9,0x3f644fac,0xbee79a5d,
0x3f7c187a,0xbe3228d4,0x3f57dc7f,0xbf099f4e,0x3f76841b,0xbe8a11f7,0x3f495521,0xbf1e1e22,0x3f6e8ff8,0xbeb9bb1e,0x3f38dd65,0xbf311722,
0x3f7f2f9d,0xbda3308c,0x3f63f473,0xbee900b7,0x3f7bf531,0xbe354098,0x3f577026,0xbf0a48ad,0x3f764d97,0xbe8b9507,0x3f48d8b3,0xbf1ebc12,
0x3f6e46be,0xbebb31a0,0x3f385216,0xbf31a81d,0x3f7f1f49,0xbda973ba,0x3f6398ac,0xbeea6681,0x3f7bd14d,0xbe3857ec,0x3f570348,0xbf0af1b7,
0x3f76167a,0xbe8d17c0,0x3f485bca,0xbf1f599f,0x3f6dfcf2,0xbebca7af,0x3f37c655,0xbf3238aa,0x3f7f0e58,0xbdafb680,0x3f633c5a,0xbeebcbbb,
0x3f7baccd,0xbe3b6ecf,0x3f5695e5,0xbf0b9a6b,0x3f75dec6,0xbe8e9a22,0x3f47de65,0xbf1ff6cb,0x3f6db293,0xbebe1d4a,0x3f373a23,0xbf32c8c9,
0x3f7efcc9,0xbdb5f8da,0x3f62df7b,0xbeed3063,0x3f7b87b2,0xbe3e853e,0x3f5627fe,0xbf0c42c9,0x3f75a67b,0xbe901c2c,0x3f476085,0xbf209393,
0x3f6d67a1,0xbebf926f,0x3f36ad7f,0xbf33587a,0x3f7eea9d,0xbdbc3ac3,0x3f628210,0xbeee9479,0x3f7b61fc,0xbe419b37,0x3f55b993,0xbf0cead0,
0x3f756d97,0xbe919ddd,0x3f46e22a,0xbf212ff9,0x3f6d1c1d,0xbec1071e,0x3f36206c,0xbf33e7bc,0x3f7ed7d4,0xbdc27c39,0x3f62241a,0xbeeff7fb,
0x3f7b3bab,0xbe44b0b9,0x3f554aa4,0xbf0d9281,0x3f75341d,0xbe931f35,0x3f466354,0xbf21cbfb,0x3f6cd007,0xbec27b55,0x3f3592e7,0xbf34768f,
0x3f3504f3,0xbf3504f3,0x3ec3ef15,0xbf6c835e,0x3f226799,0xbf45e403,0x3e94a031,0xbf74fa0b,0x3f0e39da,0xbf54db31,0x3e47c5c2,0xbf7b14be,
0x3ef15aea,0xbf61c598,0x3dc8bd36,0xbf7ec46d,0x3f34768f,0xbf3592e7,0x3ec27b55,0xbf6cd007,0x3f21cbfb,0xbf466354,0x3e931f35,0xbf75341d,
0x3f0d9281,0xbf554aa4,0x3e44b0b9,0xbf7b3bab,0x3eeff7fb,0xbf62241a,0x3dc27c39,0xbf7ed7d4,0x3f33e7bc,0xbf36206c,0x3ec1071e,0xbf6d1c1d,
0x3f212ff9,0xbf46e22a,0x3e919ddd,0xbf756d97,0x3f0cead0,0xbf55b993,0x3e419b37,0xbf7b61fc,0x3eee9479,0xbf628210,0x3dbc3ac3,0xbf7eea9d,
0x3f33587a,0xbf36ad7f,0x3ebf926f,0xbf6d67a1,0x3f209393,0xbf476085,0x3e901c2c,0xbf75a67b,0x3f0c42c9,0xbf5627fe,0x3e3e853e,0xbf7b87b2,
0x3eed3063,0xbf62df7b,0x3db5f8da,0xbf7efcc9,0x3f32c8c9,0xbf373a23,0x3ebe1d4a,0xbf6db293,0x3f1ff6cb,0xbf47de65,0x3e8e9a22,0xbf75dec6,
0x3f0b9a6b,0xbf5695e5,0x3e3b6ecf,0xbf7baccd,0x3eebcbbb,0xbf633c5a,0x3dafb680,0xbf7f0e58,0x3f3238aa,0xbf37c655,0x3ebca7af,0xbf6dfcf2,
0x3f1f599f,0xbf485bca,0x3e8d17c0,0xbf76167a,0x3f0af1b7,0xbf570348,0x3e3857ec,0xbf7bd14d,0x3eea6681,0xbf6398ac,0x3da973ba,0xbf7f1f49,
0x3f31a81d,0xbf385216,0x3ebb31a0,0xbf6e46be,0x3f1ebc12,0xbf48d8b3,0x3e8b9507,0xbf764d97,0x3f0a48ad,0xbf577026,0x3e354098,0xbf7bf531,
0x3ee900b7,0xbf63f473,0x3da3308c,0xbf7f2f9d,0x3f311722,0xbf38dd65,0x3eb9bb1e,0xbf6e8ff8,0x3f1e1e22,0xbf495521,0x3e8a11f7,0xbf76841b,
0x3f099f4e,0xbf57dc7f,0x3e3228d4,0xbf7c187a,0x3ee79a5d,0xbf644fac,0x3d9cecf9,0xbf7f3f54,0x3f3085bb,0xbf396842,0x3eb8442a,0xbf6ed89e,
0x3f1d7fd1,0xbf49d112,0x3e888e93,0xbf76ba07,0x3f08f59b,0xbf584853,0x3e2f10a2,0xbf7c3b28,0x3ee63375,0xbf64aa59,0x3d96a905,0xbf7f4e6d,
0x3f2ff3e6,0xbf39f2ac,0x3eb6ccc3,0xbf6f20b0,0x3f1ce11f,0xbf4a4c87,0x3e870ada,0xbf76ef5b,0x3f084b92,0xbf58b3a1,0x3e2bf804,0xbf7c5d3a,
0x3ee4cbfe,0xbf650479,0x3d9064b4,0xbf7f5ce9,0x3f2f61a5,0xbf3a7ca4,0x3eb554ec,0xbf6f6830,0x3f1c420c,0xbf4ac77f,0x3e8586ce,0xbf772417,
0x3f07a136,0xbf591e6a,0x3e28defc,0xbf7c7eb0,0x3ee363fa,0xbf655e0b,0x3d8a200a,0xbf7f6ac7,0x3f2ecef7,0xbf3b0629,0x3eb3dca5,0xbf6faf1b,
0x3f1ba299,0xbf4b41fa,0x3e840270,0xbf77583a,0x3f06f686,0xbf5988ad,0x3e25c58c,0xbf7c9f8a,0x3ee1fb6a,0xbf65b710,0x3d83db0a,0xbf7f7808,
0x3f2e3bde,0xbf3b8f3b,0x3eb263ef,0xbf6ff573,0x3f1b02c6,0xbf4bbbf8,0x3e827dc0,0xbf778bc5,0x3f064b82,0xbf59f26a,0x3e22abb6,0xbf7cbfc9,
0x3ee0924f,0xbf660f88,0x3d7b2b74,0xbf7f84ab,0x3f2da859,0xbf3c17d9,0x3eb0eacb,0xbf703b37,0x3f1a6293,0xbf4c3578,0x3e80f8c0,0xbf77beb7,
0x3f05a02c,0xbf5a5ba0,0x3e1f917b,0xbf7cdf6c,0x3edf28a9,0xbf666771,0x3d6ea038,0xbf7f90b1,0x3f2d1469,0xbf3ca003,0x3eaf713a,0xbf708066,
0x3f19c200,0xbf4cae79,0x3e7ee6e1,0xbf77f110,0x3f04f484,0xbf5ac450,0x3e1c76de,0xbf7cfe73,0x3eddbe79,0xbf66becc,0x3d621469,0xbf7f9c18,
0x3f2c800f,0xbf3d27b8,0x3eadf73c,0xbf70c501,0x3f19210f,0xbf4d26fd,0x3e7bdba4,0xbf7822d1,0x3f044889,0xbf5b2c79,0x3e195be0,0xbf7d1cdd,
0x3edc53c1,0xbf671599,0x3d55880e,0xbf7fa6e3,0x3f2beb4a,0xbf3daef9,0x3eac7cd4,0xbf710908,0x3f187fc0,0xbf4d9f02,0x3e78cfcc,0xbf7853f8,
0x3f039c3d,0xbf5b941a,0x3e164083,0xbf7d3aac,0x3edae880,0xbf676bd8,0x3d48fb30,0xbf7fb10f,0x3f2b561b,0xbf3e35c5,0x3eab0201,0xbf714c7a,
0x3f17de12,0xbf4e1689,0x3e75c35a,0xbf788486,0x3f02ef9f,0xbf5bfb34,0x3e1324ca,0xbf7d57de,0x3ed97cb9,0xbf67c187,0x3d3c6dd5,0xbf7fba9e,
0x3f2ac082,0xbf3ebc1b,0x3ea986c4,0xbf718f57,0x3f173c07,0xbf4e8d90,0x3e72b651,0xbf78b47b,0x3f0242b1,0xbf5c61c7,0x3e1008b7,0xbf7d7474,
0x3ed8106b,0xbf6816a8,0x3d2fe007,0xbf7fc38f,0x3f2a2a80,0xbf3f41fc,0x3ea80b1f,0xbf71d19f,0x3f16999f,0xbf4f0417,0x3e6fa8b2,0xbf78e3d6,
0x3f019573,0xbf5cc7d1,0x3e0cec4a,0xbf7d906e,0x3ed6a399,0xbf686b39,0x3d2351cb,0xbf7fcbe2,0x3f299415,0xbf3fc767,0x3ea68f12,0xbf721352,
0x3f15f6d9,0xbf4f7a1f,0x3e6c9a7f,0xbf791298,0x3f00e7e4,0xbf5d2d53,0x3e09cf86,0xbf7dabcc,0x3ed53641,0xbf68bf3c,0x3d16c32c,0xbf7fd397,
0x3f28fd41,0xbf404c5c,0x3ea5129f,0xbf725470,0x3f1553b7,0xbf4fefa8,0x3e698bba,0xbf7940c0,0x3f003a06,0xbf5d924d,0x3e06b26e,0xbf7dc68c,
0x3ed3c867,0xbf6912ae,0x3d0a342f,0xbf7fdaaf,0x3f286605,0xbf40d0da,0x3ea395c5,0xbf7294f8,0x3f14b039,0xbf5064af,0x3e667c66,0xbf796e4e,
0x3eff17b2,0xbf5df6be,0x3e039502,0xbf7de0b1,0x3ed25a09,0xbf696591,0x3cfb49ba,0xbf7fe129,0x3f27ce61,0xbf4154e1,0x3ea21887,0xbf72d4eb,
0x3f140c5f,0xbf50d937,0x3e636c83,0xbf799b43,0x3efdbabb,0xbf5e5aa6,0x3e007745,0xbf7dfa38,0x3ed0eb2a,0xbf69b7e4,0x3ce22a7a,0xbf7fe705,
0x3f273656,0xbf41d870,0x3ea09ae5,0xbf731447,0x3f13682a,0xbf514d3d,0x3e605c13,0xbf79c79d,0x3efc5d27,0xbf5ebe05,0x3dfab273,0xbf7e1324,
0x3ecf7bca,0xbf6a09a7,0x3cc90ab0,0xbf7fec43,0x3f269de3,0xbf425b89,0x3e9f1cdf,0xbf73530e,0x3f12c39a,0xbf51c0c2,0x3e5d4b1a,0xbf79f35e,
0x3efafef7,0xbf5f20db,0x3df475c0,0xbf7e2b72,0x3ece0bea,0xbf6a5ad9,0x3cafea69,0xbf7ff0e3,0x3f26050a,0xbf42de29,0x3e9d9e78,0xbf73913f,
0x3f121eb0,0xbf5233c6,0x3e5a3997,0xbf7a1e84,0x3ef9a02d,0xbf5f8327,0x3dee3876,0xbf7e4323,0x3ecc9b8b,0xbf6aab7b,0x3c96c9b6,0xbf7ff4e6,
0x3f256bcb,0xbf436051,0x3e9c1faf,0xbf73ced9,0x3f11796b,0xbf52a649,0x3e57278f,0xbf7a4910,0x3ef840c8,0xbf5fe4e9,0x3de7fa9a,0xbf7e5a38,
0x3ecb2aae,0xbf6afb8c,0x3c7b514b,0xbf7ff84a,0x3f24d225,0xbf43e200,0x3e9aa086,0xbf740bdd,0x3f10d3cd,0xbf531849,0x3e541501,0xbf7a7302,
0x3ef6e0cb,0xbf604621,0x3de1bc2e,0xbf7e70b0,0x3ec9b953,0xbf6b4b0c,0x3c490e90,0xbf7ffb11,0x3f24381a,0xbf446337,0x3e9920fe,0xbf74484b,
0x3f102dd5,0xbf5389c7,0x3e5101f1,0xbf7a9c59,0x3ef58035,0xbf60a6cf,0x3ddb7d37,0xbf7e868b,0x3ec8477c,0xbf6b99fb,0x3c16cb58,0xbf7ffd39,
0x3f239da9,0xbf44e3f5,0x3e97a117,0xbf748422,0x3f0f8784,0xbf53fac3,0x3e4dee60,0xbf7ac516,0x3ef41f07,0xbf6106f2,0x3dd53db9,0xbf7e9bc9,
0x3ec6d529,0xbf6be858,0x3bc90f88,0xbf7ffec4,0x3f2302d3,0xbf456439,0x3e9620d2,0xbf74bf62,0x3f0ee0db,0xbf546b3b,0x3e4ada4f,0xbf7aed37,
0x3ef2bd43,0xbf61668a,0x3dcefdb7,0xbf7eb069,0x3ec5625c,0xbf6c3624,0x3b490fc6,0xbf7fffb1,
};
__device__ __align__(128) const uint32_t T_TW576[1024] = {
0x3f800000,0x0,0x3f800000,0x0,0x3f800000,0x0,0x3f800000,0x0,0x3f800000,0x0,0x3f800000,0x0,
0x3f800000,0x0,0x3f800000,0x0,0x3f7ffc1a,0xbc32b7da,0x3f7ff067,0xbcb2b521,0x3f7fdce9,0xbd060472,0x3f7fc1a0,0xbd32aa3e,
0x3f7f9e8c,0xbd5f4a99,0x3f7f73af,0xbd85f213,0x3f7f4109,0xbd9c3ac6,0x3f7f069e,0xbdb27eb6,0x3f7ff067,0xbcb2b521,0x3f7fc1a0,0xbd32aa3e,
0x3f7f73af,0xbd85f213,0x3f7f069e,0xbdb27eb6,0x3f7e7a7a,0xbddef599,0x3f7dcf55,0xbe05a8a8,0x3f7d0543,0xbe1bc63c,0x3f7c1c5c,0xbe31d0d4,
0x3f7fdce9,0xbd060472,0x3f7f73af,0xbd85f213,0x3f7ec46d,0xbdc8bd36,0x3f7dcf55,0xbe05a8a8,0x3f7c94a8,0xbe26ce12,0x3f7b14be,0xbe47c5c2,
0x3f795000,0xbe6886ae,0x3f7746ea,0xbe8483ee,0x3f7fc1a0,0xbd32aa3e,0x3f7f069e,0xbdb27eb6,0x3f7dcf55,0xbe05a8a8,0x3f7c1c5c,0xbe31d0d4,
0x3f79ee89,0xbe5da259,0x3f7746ea,0xbe8483ee,0x3f7426cb,0xbe99f61c,0x3f708fb2,0xbeaf1d44,0x3f7f9e8c,0xbd5f4a99,0x3f7e7a7a,0xbddef599,
0x3f7c94a8,0xbe26ce12,0x3f79ee89,0xbe5da259,0x3f768a20,0xbe89e6f1,0x3f726a03,0xbea493b7,0x3f6d9156,0xbebec330,0x3f6803ca,0xbed8616c,
0x3f7f73af,0xbd85f213,0x3f7dcf55,0xbe05a8a8,0x3f7b14be,0xbe47c5c2,0x3f7746ea,0xbe8483ee,0x3f726a03,0xbea493b7,0x3f6c835e,0xbec3ef15,
0x3f659974,0xbee273aa,0x3f5db3d7,0xbf000000,0x3f7f4109,0xbd9c3ac6,0x3f7d0543,0xbe1bc63c,0x3f795000,0xbe6886ae,0x3f7426cb,0xbe99f61c,
0x3f6d9156,0xbebec330,0x3f659974,0xbee273aa,0x3f5c4b07,0xbf026926,0x3f51b3f3,0xbf12d5e8,0x3f7f069e,0xbdb27eb6,0x3f7c1c5c,0xbe31d0d4,
0x3f7746ea,0xbe8483ee,0x3f708fb2,0xbeaf1d44,0x3f6803ca,0xbed8616c,0x3f5db3d7,0xbf000000,0x3f51b3f3,0xbf12d5e8,0x3f441b7d,0xbf248dbb,
0x3f7ec46d,0xbdc8bd36,0x3f7b14be,0xbe47c5c2,0x3f74fa0b,0xbe94a031,0x3f6c835e,0xbec3ef15,0x3f61c598,0xbef15aea,0x3f54db31,0xbf0e39da,
0x3f45e403,0xbf226799,0x3f3504f3,0xbf3504f3,0x3f7e7a7a,0xbddef599,0x3f79ee89,0xbe5da259,0x3f726a03,0xbea493b7,0x3f6803ca,0xbed8616c,
0x3f5adb81,0xbf04ce53,0x3f4b1934,0xbf1bd7ca,0x3f38ecd8,0xbf310700,0x3f248dbb,0xbf441b7d,0x3f7e28c6,0xbdf52731,0x3f78a9e0,0xbe7363ee,
0x3f6f9788,0xbeb45a1e,0x3f631324,0xbeec6a50,0x3f534aca,0xbf108a14,0x3f407893,0xbf28cae3,0x3f2ae1c9,0xbf3e9e4b,0x3f12d5e8,0xbf51b3f3,
0x3f7dcf55,0xbe05a8a8,0x3f7746ea,0xbe8483ee,0x3f6c835e,0xbec3ef15,0x3f5db3d7,0xbf000000,0x3f4b1934,0xbf1bd7ca,0x3f3504f3,0xbf3504f3,
0x3f1bd7ca,0xbf4b1934,0x3f000000,0xbf5db3d7,0x3f7d6e28,0xbe10b9a6,0x3f75c5d4,0xbe8f45c0,0x3f692e5f,0xbed34e56,0x3f57e880,0xbf098c78,
0x3f424cfe,0xbf26aed9,0x3f28cae3,0xbf407893,0x3f0be54a,0xbf56651d,0x3ed8616c,0xbf6803ca,0x3f7d0543,0xbe1bc63c,0x3f7426cb,0xbe99f61c,
0x3f659974,0xbee273aa,0x3f51b3f3,0xbf12d5e8,0x3f38ecd8,0xbf310700,0x3f1bd7ca,0xbf4b1934,0x3ef64429,0xbf60712a,0x3eaf1d44,0xbf708fb2,
0x3f7c94a8,0xbe26ce12,0x3f726a03,0xbea493b7,0x3f61c598,0xbef15aea,0x3f4b1934,0xbf1bd7ca,0x3f2effe8,0xbf3ad85f,0x3f0e39da,0xbf54db31,
0x3ed34e56,0xbf692e5f,0x3e8483ee,0xbf7746ea,0x3f7c1c5c,0xbe31d0d4,0x3f708fb2,0xbeaf1d44,0x3f5db3d7,0xbf000000,0x3f441b7d,0xbf248dbb,
0x3f248dbb,0xbf441b7d,0x3f000000,0xbf5db3d7,0x3eaf1d44,0xbf708fb2,0x3e31d0d4,0xbf7c1c5c,0x3f7b9c62,0xbe3cce2b,0x3f6e9811,0xbeb9917b,
0x3f596550,0xbf072f74,0x3f3cbe35,0xbf2cf37b,0x3f199e45,0xbf4cc94c,0x3ee273aa,0xbf659974,0x3e89e6f1,0xbf768a20,0x3db27eb6,0xbf7f069e,
0x3f7b14be,0xbe47c5c2,0x3f6c835e,0xbec3ef15,0x3f54db31,0xbf0e39da,0x3f3504f3,0xbf3504f3,0x3f0e39da,0xbf54db31,0x3ec3ef15,0xbf6c835e,
0x3e47c5c2,0xbf7b14be,0x0,0xbf800000,0x3f7a8575,0xbe52b743,0x3f6a51da,0xbece34d0,0x3f5016b8,0xbf151d42,0x3f2cf37b,0xbf3cbe35,
0x3f026926,0xbf5c4b07,0x3ea493b7,0xbf726a03,0x3df52731,0xbf7e28c6,0xbdb27eb6,0xbf7f069e,0x3f79ee89,0xbe5da259,0x3f6803ca,0xbed8616c,
0x3f4b1934,0xbf1bd7ca,0x3f248dbb,0xbf441b7d,0x3eec6a50,0xbf631324,0x3e8483ee,0xbf7746ea,0x3d32aa3e,0xbf7fc1a0,0xbe31d0d4,0xbf7c1c5c,
0x3f795000,0xbe6886ae,0x3f659974,0xbee273aa,0x3f45e403,0xbf226799,0x3f1bd7ca,0xbf4b1934,0x3ed34e56,0xbf692e5f,0x3e47c5c2,0xbf7b14be,
0xbd060472,0xbf7fdce9,0xbe8483ee,0xbf7746ea,0x3f78a9e0,0xbe7363ee,0x3f631324,0xbeec6a50,0x3f407893,0xbf28cae3,0x3f12d5e8,0xbf51b3f3,
0x3eb9917b,0xbf6e9811,0x3e05a8a8,0xbf7dcf55,0xbddef599,0xbf7e7a7a,0xbeaf1d44,0xbf708fb2,0x3f77fc2c,0xbe7e39c4,0x3f60712a,0xbef64429,
0x3f3ad85f,0xbf2effe8,0x3f098c78,0xbf57e880,0x3e9f4757,0xbf734c1c,0x3d85f213,0xbf7f73af,0xbe3cce2b,0xbf7b9c62,0xbed8616c,0xbf6803ca,
0x3f7746ea,0xbe8483ee,0x3f5db3d7,0xbf000000,0x3f3504f3,0xbf3504f3,0x3f000000,0xbf5db3d7,0x3e8483ee,0xbf7746ea,0x0,0xbf800000,
0xbe8483ee,0xbf7746ea,0xbf000000,0xbf5db3d7,0x3f768a20,0xbe89e6f1,0x3f5adb81,0xbf04ce53,0x3f2effe8,0xbf3ad85f,0x3eec6a50,0xbf631324,
0x3e52b743,0xbf7a8575,0xbd85f213,0xbf7f73af,0xbea9db13,0xbf718088,0xbf12d5e8,0xbf51b3f3,0x3f75c5d4,0xbe8f45c0,0x3f57e880,0xbf098c78,
0x3f28cae3,0xbf407893,0x3ed8616c,0xbf6803ca,0x3e1bc63c,0xbf7d0543,0xbe05a8a8,0xbf7dcf55,0xbece34d0,0xbf6a51da,0xbf248dbb,0xbf441b7d,
0x3f74fa0b,0xbe94a031,0x3f54db31,0xbf0e39da,0x3f226799,0xbf45e403,0x3ec3ef15,0xbf6c835e,0x3dc8bd36,0xbf7ec46d,0xbe47c5c2,0xbf7b14be,
0xbef15aea,0xbf61c598,0xbf3504f3,0xbf3504f3,0x3f7426cb,0xbe99f61c,0x3f51b3f3,0xbf12d5e8,0x3f1bd7ca,0xbf4b1934,0x3eaf1d44,0xbf708fb2,
0x3d32aa3e,0xbf7fc1a0,0xbe8483ee,0xbf7746ea,0xbf098c78,0xbf57e880,0xbf441b7d,0xbf248dbb,0x3f734c1c,0xbe9f4757,0x3f4e7327,0xbf176012,
0x3f151d42,0xbf5016b8,0x3e99f61c,0xbf7426cb,0xbc32b7da,0xbf7ffc1a,0xbea493b7,0xbf726a03,0xbf199e45,0xbf4cc94c,0xbf51b3f3,0xbf12d5e8,
0x3f726a03,0xbea493b7,0x3f4b1934,0xbf1bd7ca,0x3f0e39da,0xbf54db31,0x3e8483ee,0xbf7746ea,0xbd85f213,0xbf7f73af,0xbec3ef15,0xbf6c835e,
0xbf28cae3,0xbf407893,0xbf5db3d7,0xbf000000,0x3f718088,0xbea9db13,0x3f47a682,0xbf203c85,0x3f072f74,0xbf596550,0x3e5da259,0xbf79ee89,
0xbdf52731,0xbf7e28c6,0xbee273aa,0xbf659974,0xbf36fbaf,0xbf3308b4,0xbf6803ca,0xbed8616c,0x3f708fb2,0xbeaf1d44,0x3f441b7d,0xbf248dbb,
0x3f000000,0xbf5db3d7,0x3e31d0d4,0xbf7c1c5c,0xbe31d0d4,0xbf7c1c5c,0xbf000000,0xbf5db3d7,0xbf441b7d,0xbf248dbb,0xbf708fb2,0xbeaf1d44,
0x3f6f9788,0xbeb45a1e,0x3f407893,0xbf28cae3,0x3ef15aea,0xbf61c598,0x3e05a8a8,0xbf7dcf55,0xbe6886ae,0xbf795000,0xbf0e39da,0xbf54db31,
0xbf5016b8,0xbf151d42,0xbf7746ea,0xbe8483ee,0x3f6e9811,0xbeb9917b,0x3f3cbe35,0xbf2cf37b,0x3ee273aa,0xbf659974,0x3db27eb6,0xbf7f069e,
0xbe8f45c0,0xbf75c5d4,0xbf1bd7ca,0xbf4b1934,0xbf5adb81,0xbf04ce53,0xbf7c1c5c,0xbe31d0d4,0x3f6d9156,0xbebec330,0x3f38ecd8,0xbf310700,
0x3ed34e56,0xbf692e5f,0x3d32aa3e,0xbf7fc1a0,0xbea9db13,0xbf718088,0xbf28cae3,0xbf407893,0xbf6459c6,0xbee77284,0xbf7f069e,0xbdb27eb6,
0x3f6c835e,0xbec3ef15,0x3f3504f3,0xbf3504f3,0x3ec3ef15,0xbf6c835e,0x0,0xbf800000,0xbec3ef15,0xbf6c835e,0xbf3504f3,0xbf3504f3,
0xbf6c835e,0xbec3ef15,0xbf800000,0x0,0x3f6b6e32,0xbec91503,0x3f310700,0xbf38ecd8,0x3eb45a1e,0xbf6f9788,0xbd32aa3e,0xbf7fc1a0,
0xbedd6dea,0xbf66d223,0xbf407893,0xbf28cae3,0xbf734c1c,0xbe9f4757,0xbf7f069e,0x3db27eb6,0x3f6a51da,0xbece34d0,0x3f2cf37b,0xbf3cbe35,
0x3ea493b7,0xbf726a03,0xbdb27eb6,0xbf7f069e,0xbef64429,0xbf60712a,0xbf4b1934,0xbf1bd7ca,0xbf78a9e0,0xbe7363ee,0xbf7c1c5c,0x3e31d0d4,
0x3f692e5f,0xbed34e56,0x3f28cae3,0xbf407893,0x3e94a031,0xbf74fa0b,0xbe05a8a8,0xbf7dcf55,0xbf072f74,0xbf596550,0xbf54db31,0xbf0e39da,
0xbf7c94a8,0xbe26ce12,0xbf7746ea,0x3e8483ee,0x3f6803ca,0xbed8616c,0x3f248dbb,0xbf441b7d,0x3e8483ee,0xbf7746ea,0xbe31d0d4,0xbf7c1c5c,
0xbf12d5e8,0xbf51b3f3,0xbf5db3d7,0xbf000000,0xbf7f069e,0xbdb27eb6,0xbf708fb2,0x3eaf1d44,0x3f66d223,0xbedd6dea,0x3f203c85,0xbf47a682,
0x3e6886ae,0xbf795000,0xbe5da259,0xbf79ee89,0xbf1e0c90,0xbf4962ed,0xbf659974,0xbee273aa,0xbf7ffc1a,0xbc32b7da,0xbf6803ca,0x3ed8616c,
0x3f659974,0xbee273aa,0x3f1bd7ca,0xbf4b1934,0x3e47c5c2,0xbf7b14be,0xbe8483ee,0xbf7746ea,0xbf28cae3,0xbf407893,0xbf6c835e,0xbec3ef15,
0xbf7f73af,0x3d85f213,0xbf5db3d7,0x3f000000,0x3f6459c6,0xbee77284,0x3f176012,0xbf4e7327,0x3e26ce12,0xbf7c94a8,0xbe99f61c,0xbf7426cb,
0xbf3308b4,0xbf36fbaf,0xbf726a03,0xbea493b7,0xbf7d6e28,0x3e10b9a6,0xbf51b3f3,0x3f12d5e8,0x3f631324,0xbeec6a50,0x3f12d5e8,0xbf51b3f3,
0x3e05a8a8,0xbf7dcf55,0xbeaf1d44,0xbf708fb2,0xbf3cbe35,0xbf2cf37b,0xbf7746ea,0xbe8483ee,0xbf79ee89,0x3e5da259,0xbf441b7d,0x3f248dbb,
0x3f61c598,0xbef15aea,0x3f0e39da,0xbf54db31,0x3dc8bd36,0xbf7ec46d,0xbec3ef15,0xbf6c835e,0xbf45e403,0xbf226799,0xbf7b14be,0xbe47c5c2,
0xbf74fa0b,0x3e94a031,0xbf3504f3,0x3f3504f3,0x3f60712a,0xbef64429,0x3f098c78,0xbf57e880,0x3d85f213,0xbf7f73af,0xbed8616c,0xbf6803ca,
0xbf4e7327,0xbf176012,0xbf7dcf55,0xbe05a8a8,0xbf6e9811,0x3eb9917b,0xbf248dbb,0x3f441b7d,0x3f5f15e7,0xbefb25e8,0x3f04ce53,0xbf5adb81,
0x3d060472,0xbf7fdce9,0xbeec6a50,0xbf631324,0xbf56651d,0xbf0be54a,0xbf7f73af,0xbd85f213,0xbf66d223,0x3edd6dea,0xbf12d5e8,0x3f51b3f3,
0x3f5db3d7,0xbf000000,0x3f000000,0xbf5db3d7,0x0,0xbf800000,0xbf000000,0xbf5db3d7,0xbf5db3d7,0xbf000000,0xbf800000,0x0,
0xbf5db3d7,0x3f000000,0xbf000000,0x3f5db3d7,0x3f5c4b07,0xbf026926,0x3ef64429,0xbf60712a,0xbd060472,0xbf7fdce9,0xbf098c78,0xbf57e880,
0xbf6459c6,0xbee77284,0xbf7f73af,0x3d85f213,0xbf534aca,0x3f108a14,0xbed8616c,0x3f6803ca,0x3f5adb81,0xbf04ce53,0x3eec6a50,0xbf631324,
0xbd85f213,0xbf7f73af,0xbf12d5e8,0xbf51b3f3,0xbf6a51da,0xbece34d0,0xbf7dcf55,0x3e05a8a8,0xbf47a682,0x3f203c85,0xbeaf1d44,0x3f708fb2,
0x3f596550,0xbf072f74,0x3ee273aa,0xbf659974,0xbdc8bd36,0xbf7ec46d,0xbf1bd7ca,0xbf4b1934,0xbf6f9788,0xbeb45a1e,0xbf7b14be,0x3e47c5c2,
0xbf3ad85f,0x3f2effe8,0xbe8483ee,0x3f7746ea,0x3f57e880,0xbf098c78,0x3ed8616c,0xbf6803ca,0xbe05a8a8,0xbf7dcf55,0xbf248dbb,0xbf441b7d,
0xbf7426cb,0xbe99f61c,0xbf7746ea,0x3e8483ee,0xbf2cf37b,0x3f3cbe35,0xbe31d0d4,0x3f7c1c5c,0x3f56651d,0xbf0be54a,0x3ece34d0,0xbf6a51da,
0xbe26ce12,0xbf7c94a8,0xbf2cf37b,0xbf3cbe35,0xbf77fc2c,0xbe7e39c4,0xbf726a03,0x3ea493b7,0xbf1e0c90,0x3f4962ed,0xbdb27eb6,0x3f7f069e,
0x3f54db31,0xbf0e39da,0x3ec3ef15,0xbf6c835e,0xbe47c5c2,0xbf7b14be,0xbf3504f3,0xbf3504f3,0xbf7b14be,0xbe47c5c2,0xbf6c835e,0x3ec3ef15,
0xbf0e39da,0x3f54db31,0x0,0x3f800000,0x3f534aca,0xbf108a14,0x3eb9917b,0xbf6e9811,0xbe6886ae,0xbf795000,0xbf3cbe35,0xbf2cf37b,
0xbf7d6e28,0xbe10b9a6,0xbf659974,0x3ee273aa,0xbefb25e8,0x3f5f15e7,0x3db27eb6,0x3f7f069e,0x3f51b3f3,0xbf12d5e8,0x3eaf1d44,0xbf708fb2,
0xbe8483ee,0xbf7746ea,0xbf441b7d,0xbf248dbb,0xbf7f069e,0xbdb27eb6,0xbf5db3d7,0x3f000000,0xbed8616c,0x3f6803ca,0x3e31d0d4,0x3f7c1c5c,
0x3f5016b8,0xbf151d42,0x3ea493b7,0xbf726a03,0xbe94a031,0xbf74fa0b,0xbf4b1934,0xbf1bd7ca,0xbf7fdce9,0xbd060472,0xbf54db31,0x3f0e39da,
0xbeb45a1e,0x3f6f9788,0x3e8483ee,0x3f7746ea,0x3f4e7327,0xbf176012,0x3e99f61c,0xbf7426cb,0xbea493b7,0xbf726a03,0xbf51b3f3,0xbf12d5e8,
0xbf7ff067,0x3cb2b521,0xbf4b1934,0x3f1bd7ca,0xbe8f45c0,0x3f75c5d4,0x3eaf1d44,0x3f708fb2,0x3f4cc94c,0xbf199e45,0x3e8f45c0,0xbf75c5d4,
0xbeb45a1e,0xbf6f9788,0xbf57e880,0xbf098c78,0xbf7f4109,0x3d9c3ac6,0xbf407893,0x3f28cae3,0xbe52b743,0x3f7a8575,0x3ed8616c,0x3f6803ca,
0x3f4b1934,0xbf1bd7ca,0x3e8483ee,0xbf7746ea,0xbec3ef15,0xbf6c835e,0xbf5db3d7,0xbf000000,0xbf7dcf55,0x3e05a8a8,0xbf3504f3,0x3f3504f3,
0xbe05a8a8,0x3f7dcf55,0x3f000000,0x3f5db3d7,0x3f4962ed,0xbf1e0c90,0x3e7363ee,0xbf78a9e0,0xbed34e56,0xbf692e5f,0xbf631324,0xbeec6a50,
0xbf7b9c62,0x3e3cce2b,0xbf28cae3,0x3f407893,0xbd5f4a99,0x3f7f9e8c,0x3f12d5e8,0x3f51b3f3,0x3f47a682,0xbf203c85,0x3e5da259,0xbf79ee89,
0xbee273aa,0xbf659974,0xbf6803ca,0xbed8616c,0xbf78a9e0,0x3e7363ee,0xbf1bd7ca,0x3f4b1934,0x3cb2b521,0x3f7ff067,0x3f248dbb,0x3f441b7d,
0x3f45e403,0xbf226799,0x3e47c5c2,0xbf7b14be,0xbef15aea,0xbf61c598,0xbf6c835e,0xbec3ef15,0xbf74fa0b,0x3e94a031,0xbf0e39da,0x3f54db31,
0x3dc8bd36,0x3f7ec46d,0x3f3504f3,0x3f3504f3,
};

__device__ __align__(1024) uint32_t g_mod[3 * D_];
__device__ __align__(1024) uint4 g_WT[DF_ * 512];
__device__ __align__(1024) uint32_t g_Z1[2 * DF_ * 1024];
__device__ __align__(1024) uint32_t g_Z2[128 * 5120];
__device__ __align__(1024) uint32_t g_x1[S_ * D_ / 2];
__device__ __align__(1024) uint8_t g_h3[32 * 18 * 4096];
__device__ __align__(1024) uint8_t g_u[72 * D_ * 128];
#define ROT1 0
#define ZSLEEP 2000
#define ZS2 300
#define HSLEEP 40
#define FSLEEP 0
#define PF2 8
#define PF2K 16
#define HOLDA 3
#define GOAT 1
#define HOLD1 0
#define PFMODE 1
#define PFKB 8
#define NG1 4
enum { C_MODA = 0, C_MODB = 8, C_WT = 16, C_Z1 = 24, C_Z2 = 32, C_DONE = 40, C_H3 = 64, C_U = 96, C_P = 192, C_TOTAL = 256 };
__device__ __align__(1024) unsigned g_cnt[C_TOTAL];

#define TE(k) do {} while (0)
#define TD(k) do {} while (0)
#define TC(k) do {} while (0)
#define TS(k) do {} while (0)
#define TSC(k) do {} while (0)
#define SKIPN(x) (x)
#define U_SIGNAL signal_rlx
struct Maps { CUtensorMap w1, w2, x1, out, z1, z2, wm; };
struct Params {
  const __nv_bfloat16 *x, *wr, *wi, *b1, *b2, *c, *wmod, *w1, *w2;
  __nv_bfloat16* out;
};

__device__ __forceinline__ uint32_t smem_u32(const void* p) { return (uint32_t)__cvta_generic_to_shared(p); }
__device__ __forceinline__ void mbar_init(uint32_t b, int c) { asm volatile("mbarrier.init.shared::cta.b64 [%0], %1;" ::"r"(b), "r"(c)); }
__device__ __forceinline__ void mbar_expect(uint32_t b, int bytes) { asm volatile("mbarrier.arrive.expect_tx.shared::cta.b64 _, [%0], %1;" ::"r"(b), "r"(bytes) : "memory"); }
__device__ __forceinline__ void mbar_arrive(uint32_t b) { asm volatile("mbarrier.arrive.shared::cta.b64 _, [%0];" ::"r"(b) : "memory"); }
__device__ __forceinline__ bool mbar_try(uint32_t b, int ph) {
  uint32_t ok;
  asm volatile("{\n.reg .pred p;\nmbarrier.try_wait.parity.shared::cta.b64 p, [%1], %2;\nselp.u32 %0, 1, 0, p;\n}\n" : "=r"(ok) : "r"(b), "r"(ph) : "memory");
  return ok;
}
__device__ __forceinline__ void mbar_wait(uint32_t b, int ph) {
  if (__builtin_expect(!mbar_try(b, ph), 0)) {
    int it = 0;
    while (!mbar_try(b, ph)) if (++it > (1 << 22)) __trap();
  }
}
__device__ __forceinline__ void mbar_wait_cluster(uint32_t b, int ph) {
  uint32_t ok; int it = 0;
  do {
    asm volatile("{\n.reg .pred p;\nmbarrier.try_wait.parity.acquire.cluster.shared::cta.b64 p, [%1], %2;\nselp.u32 %0, 1, 0, p;\n}\n" : "=r"(ok) : "r"(b), "r"(ph) : "memory");
    if (!ok && ++it > (1 << 22)) __trap();
  } while (!ok);
}
__device__ __forceinline__ void tma2d(uint32_t dst, const CUtensorMap* m, int c0, int c1, uint32_t bar) {
  asm volatile("cp.async.bulk.tensor.2d.shared::cluster.global.mbarrier::complete_tx::bytes [%0], [%1, {%3, %4}], [%2];" ::"r"(dst), "l"(m), "r"(bar), "r"(c0), "r"(c1) : "memory");
}
#define EF 3
__device__ __forceinline__ uint64_t pol_ef() { uint64_t p; asm("createpolicy.fractional.L2::evict_first.b64 %0, 1.0;" : "=l"(p)); return p; }
__device__ __forceinline__ void tma2d_h(uint32_t dst, const CUtensorMap* m, int c0, int c1, uint32_t bar) {
  asm volatile("cp.async.bulk.tensor.2d.shared::cluster.global.mbarrier::complete_tx::bytes.L2::cache_hint [%0], [%1, {%3, %4}], [%2], %5;" ::"r"(dst), "l"(m), "r"(bar), "r"(c0), "r"(c1), "l"(pol_ef()) : "memory");
}
__device__ __forceinline__ void tma2d_mc_h(uint32_t dst, const CUtensorMap* m, int c0, int c1, uint32_t bar) {
  asm volatile("cp.async.bulk.tensor.2d.shared::cluster.global.mbarrier::complete_tx::bytes.multicast::cluster.L2::cache_hint [%0], [%1, {%3, %4}], [%2], %5, %6;" ::"r"(dst), "l"(m), "r"(bar), "r"(c0), "r"(c1), "h"((uint16_t)3), "l"(pol_ef()) : "memory");
}
__device__ __forceinline__ void bulk_ld(uint32_t dst, const void* src, int bytes, uint32_t bar) {
  asm volatile("cp.async.bulk.shared::cluster.global.mbarrier::complete_tx::bytes [%0], [%1], %2, [%3];" ::"r"(dst), "l"(src), "r"(bytes), "r"(bar) : "memory");
}
__device__ __forceinline__ void bulk_st(void* dst, uint32_t src, int bytes) {
  asm volatile("cp.async.bulk.global.shared::cta.bulk_group [%0], [%1], %2;" ::"l"(dst), "r"(src), "r"(bytes) : "memory");
}
__device__ __forceinline__ void tma_st2d(const CUtensorMap* m, uint32_t src, int c0, int c1) {
  asm volatile("cp.async.bulk.tensor.2d.global.shared::cta.bulk_group [%0, {%2, %3}], [%1];" ::"l"(m), "r"(src), "r"(c0), "r"(c1) : "memory");
}
__device__ __forceinline__ void tma_st3d(const CUtensorMap* m, uint32_t src, int c0, int c1, int c2) {
  asm volatile("cp.async.bulk.tensor.3d.global.shared::cta.bulk_group [%0, {%2, %3, %4}], [%1];" ::"l"(m), "r"(src), "r"(c0), "r"(c1), "r"(c2) : "memory");
}
__device__ __forceinline__ void bulk_commit_wait_read() {
  asm volatile("cp.async.bulk.commit_group;" ::: "memory");
  asm volatile("cp.async.bulk.wait_group.read 0;" ::: "memory");
}
__device__ __forceinline__ void bulk_commit_wait() {
  asm volatile("cp.async.bulk.commit_group;" ::: "memory");
  asm volatile("cp.async.bulk.wait_group 0;" ::: "memory");
}
__device__ __forceinline__ void prefetch_l2(const void* p, int bytes) {
  asm volatile("cp.async.bulk.prefetch.L2.global [%0], %1;" ::"l"(p), "r"(bytes) : "memory");
}
__device__ __forceinline__ uint64_t mkdesc(uint32_t addr, uint32_t lbo, uint32_t sbo, int swz) {
  return (uint64_t)((addr & 0x3FFFF) >> 4) | ((uint64_t)(lbo >> 4) << 16) | ((uint64_t)(sbo >> 4) << 32) | ((uint64_t)swz << 62);
}
__device__ __forceinline__ void wg_fence() { asm volatile("wgmma.fence.sync.aligned;" ::: "memory"); }
__device__ __forceinline__ void wg_commit() { asm volatile("wgmma.commit_group.sync.aligned;" ::: "memory"); }
template <int N> __device__ __forceinline__ void wg_wait() { asm volatile("wgmma.wait_group.sync.aligned %0;" ::"n"(N) : "memory"); }
template <int N> __device__ __forceinline__ void reg_fence(float (&d)[N]) {
#pragma unroll
  for (int i = 0; i < N; i++) asm volatile("" : "+f"(d[i])::"memory");
}
__device__ __forceinline__ void fence_async_smem() { asm volatile("fence.proxy.async.shared::cta;" ::: "memory"); }
__device__ __forceinline__ void fence_async_glb() { asm volatile("fence.proxy.async.global;" ::: "memory"); }
__device__ __forceinline__ void tma2d_mc(uint32_t dst, const CUtensorMap* m, int c0, int c1, uint32_t bar) {
  asm volatile("cp.async.bulk.tensor.2d.shared::cluster.global.mbarrier::complete_tx::bytes.multicast::cluster [%0], [%1, {%3, %4}], [%2], %5;" ::"r"(dst), "l"(m), "r"(bar), "r"(c0), "r"(c1), "h"((uint16_t)3) : "memory");
}
__device__ __forceinline__ void bulk_ld_mc(uint32_t dst, const void* src, int bytes, uint32_t bar) {
  asm volatile("cp.async.bulk.shared::cluster.global.mbarrier::complete_tx::bytes.multicast::cluster [%0], [%1], %2, [%3], %4;" ::"r"(dst), "l"(src), "r"(bytes), "r"(bar), "h"((uint16_t)3) : "memory");
}
__device__ __forceinline__ void tma_prefetch2d(const CUtensorMap* m, int c0, int c1) {
  asm volatile("cp.async.bulk.prefetch.tensor.2d.L2.global [%0, {%1, %2}];" ::"l"(m), "r"(c0), "r"(c1) : "memory");
}
__device__ __forceinline__ void release_slot(uint32_t bar) {
  const uint32_t t = threadIdx.x & 127;
  if (t < 2) asm volatile("{\n.reg .b32 r;\nmapa.shared::cluster.u32 r, %0, %1;\nmbarrier.arrive.shared::cluster.b64 _, [r];\n}" ::"r"(bar), "r"(t) : "memory");
}
__device__ __forceinline__ void cluster_sync() { asm volatile("barrier.cluster.arrive.relaxed.aligned;\nbarrier.cluster.wait.aligned;" ::: "memory"); }
__device__ __forceinline__ uint4 ld_rlx4(const void* p) { uint4 v; asm volatile("ld.global.cg.v4.b32 {%0,%1,%2,%3}, [%4];" : "=r"(v.x), "=r"(v.y), "=r"(v.z), "=r"(v.w) : "l"(p) : "memory"); return v; }
__device__ __forceinline__ uint32_t ld_rlx(const void* p) { uint32_t v; asm volatile("ld.global.cg.b32 %0, [%1];" : "=r"(v) : "l"(p) : "memory"); return v; }
__device__ __forceinline__ uint32_t nz(uint32_t w) { return w ? w : 0x8000u; }
__device__ __forceinline__ bool ok4(const uint4& v) { return (v.x != 0) & (v.y != 0) & (v.z != 0) & (v.w != 0); }
__device__ __forceinline__ void spin_guard(int& it) { asm volatile("fence.acq_rel.cta;" ::: "memory"); if (++it > (1 << 20)) __trap(); }
__device__ __forceinline__ void bar_sync(int id, int n) { asm volatile("bar.sync %0, %1;" ::"r"(id), "r"(n) : "memory"); }
__device__ __forceinline__ unsigned ld_acquire(const unsigned* p) { unsigned v; asm volatile("ld.relaxed.gpu.global.u32 %0, [%1];" : "=r"(v) : "l"(p) : "memory"); return v; }
__device__ __forceinline__ void signal_rlx(unsigned* p) { asm volatile("red.relaxed.gpu.global.add.u32 [%0], 1;" ::"l"(p) : "memory"); }
__device__ __forceinline__ void wait_cnt(const unsigned* p, unsigned target) {
  int it = 0;
  while (ld_acquire(p) < target) { if (++it > (1 << 21)) __trap(); }
}
__device__ __forceinline__ void wait_hint(const unsigned* p, unsigned target) {
  int it = 0;
  while (ld_acquire(p) < target) { __nanosleep(HSLEEP); if (++it > (1 << 21)) __trap(); }
}
__device__ __forceinline__ void signal_cnt(unsigned* p) { asm volatile("red.release.gpu.global.add.u32 [%0], 1;" ::"l"(p) : "memory"); }
__device__ __forceinline__ uint32_t pack_bf16(float lo, float hi) { uint32_t r; asm("cvt.rn.bf16x2.f32 %0, %1, %2;" : "=r"(r) : "f"(hi), "f"(lo)); return r; }
__device__ __forceinline__ float bf_lo(uint32_t v) { return __uint_as_float(v << 16); }
__device__ __forceinline__ float bf_hi(uint32_t v) { return __uint_as_float(v & 0xffff0000u); }
__device__ __forceinline__ uint32_t hadd2(uint32_t a, uint32_t b) { uint32_t r; asm("add.rn.bf16x2 %0, %1, %2;" : "=r"(r) : "r"(a), "r"(b)); return r; }
__device__ __forceinline__ uint32_t hmul2(uint32_t a, uint32_t b) { uint32_t r; asm("mul.rn.bf16x2 %0, %1, %2;" : "=r"(r) : "r"(a), "r"(b)); return r; }
__device__ __forceinline__ float rbf(float x) { uint32_t r; asm("cvt.rn.bf16x2.f32 %0, %1, %2;" : "=r"(r) : "f"(x), "f"(0.0f)); return __uint_as_float(r); }
__device__ __forceinline__ void stmatrix4(uint32_t a, uint32_t r0, uint32_t r1, uint32_t r2, uint32_t r3) {
  asm volatile("stmatrix.sync.aligned.m8n8.x4.shared.b16 [%0], {%1,%2,%3,%4};" ::"r"(a), "r"(r0), "r"(r1), "r"(r2), "r"(r3) : "memory");
}
__device__ __forceinline__ void stmatrix4t(uint32_t a, uint32_t r0, uint32_t r1, uint32_t r2, uint32_t r3) {
  asm volatile("stmatrix.sync.aligned.m8n8.x4.trans.shared.b16 [%0], {%1,%2,%3,%4};" ::"r"(a), "r"(r0), "r"(r1), "r"(r2), "r"(r3) : "memory");
}
__device__ __forceinline__ float warp_sum(float v) {
#pragma unroll
  for (int o = 16; o; o >>= 1) v += __shfl_xor_sync(0xffffffffu, v, o);
  return v;
}
__device__ __forceinline__ float2 cmul(float2 a, float2 b) { return make_float2(a.x * b.x - a.y * b.y, a.x * b.y + a.y * b.x); }

template<int TB> __device__ __forceinline__ void wgmma_ss_160_0(float (&d)[80], uint32_t al, uint32_t ah, uint32_t bl, uint32_t bh) {
  asm volatile("{\n.reg .b64 da, db;\nmov.b64 da, {%80, %81};\nmov.b64 db, {%82, %83};\n"
    "wgmma.mma_async.sync.aligned.m64n160k16.f32.bf16.bf16 {%0,%1,%2,%3,%4,%5,%6,%7,%8,%9,%10,%11,%12,%13,%14,%15,%16,%17,%18,%19,%20,%21,%22,%23,%24,%25,%26,%27,%28,%29,%30,%31,%32,%33,%34,%35,%36,%37,%38,%39,%40,%41,%42,%43,%44,%45,%46,%47,%48,%49,%50,%51,%52,%53,%54,%55,%56,%57,%58,%59,%60,%61,%62,%63,%64,%65,%66,%67,%68,%69,%70,%71,%72,%73,%74,%75,%76,%77,%78,%79}, da, db, 1, 1, 1, 1, %84;\n}\n"
    : "+f"(d[0]),"+f"(d[1]),"+f"(d[2]),"+f"(d[3]),"+f"(d[4]),"+f"(d[5]),"+f"(d[6]),"+f"(d[7]),"+f"(d[8]),"+f"(d[9]),"+f"(d[10]),"+f"(d[11]),"+f"(d[12]),"+f"(d[13]),"+f"(d[14]),"+f"(d[15]),"+f"(d[16]),"+f"(d[17]),"+f"(d[18]),"+f"(d[19]),"+f"(d[20]),"+f"(d[21]),"+f"(d[22]),"+f"(d[23]),"+f"(d[24]),"+f"(d[25]),"+f"(d[26]),"+f"(d[27]),"+f"(d[28]),"+f"(d[29]),"+f"(d[30]),"+f"(d[31]),"+f"(d[32]),"+f"(d[33]),"+f"(d[34]),"+f"(d[35]),"+f"(d[36]),"+f"(d[37]),"+f"(d[38]),"+f"(d[39]),"+f"(d[40]),"+f"(d[41]),"+f"(d[42]),"+f"(d[43]),"+f"(d[44]),"+f"(d[45]),"+f"(d[46]),"+f"(d[47]),"+f"(d[48]),"+f"(d[49]),"+f"(d[50]),"+f"(d[51]),"+f"(d[52]),"+f"(d[53]),"+f"(d[54]),"+f"(d[55]),"+f"(d[56]),"+f"(d[57]),"+f"(d[58]),"+f"(d[59]),"+f"(d[60]),"+f"(d[61]),"+f"(d[62]),"+f"(d[63]),"+f"(d[64]),"+f"(d[65]),"+f"(d[66]),"+f"(d[67]),"+f"(d[68]),"+f"(d[69]),"+f"(d[70]),"+f"(d[71]),"+f"(d[72]),"+f"(d[73]),"+f"(d[74]),"+f"(d[75]),"+f"(d[76]),"+f"(d[77]),"+f"(d[78]),"+f"(d[79])
    : "r"(al), "r"(ah), "r"(bl), "r"(bh), "n"(TB));
}
template<int TB> __device__ __forceinline__ void wgmma_ss_144_0(float (&d)[80], uint32_t al, uint32_t ah, uint32_t bl, uint32_t bh) {
  asm volatile("{\n.reg .b64 da, db;\nmov.b64 da, {%72, %73};\nmov.b64 db, {%74, %75};\n"
    "wgmma.mma_async.sync.aligned.m64n144k16.f32.bf16.bf16 {%0,%1,%2,%3,%4,%5,%6,%7,%8,%9,%10,%11,%12,%13,%14,%15,%16,%17,%18,%19,%20,%21,%22,%23,%24,%25,%26,%27,%28,%29,%30,%31,%32,%33,%34,%35,%36,%37,%38,%39,%40,%41,%42,%43,%44,%45,%46,%47,%48,%49,%50,%51,%52,%53,%54,%55,%56,%57,%58,%59,%60,%61,%62,%63,%64,%65,%66,%67,%68,%69,%70,%71}, da, db, 1, 1, 1, 1, %76;\n}\n"
    : "+f"(d[0]),"+f"(d[1]),"+f"(d[2]),"+f"(d[3]),"+f"(d[4]),"+f"(d[5]),"+f"(d[6]),"+f"(d[7]),"+f"(d[8]),"+f"(d[9]),"+f"(d[10]),"+f"(d[11]),"+f"(d[12]),"+f"(d[13]),"+f"(d[14]),"+f"(d[15]),"+f"(d[16]),"+f"(d[17]),"+f"(d[18]),"+f"(d[19]),"+f"(d[20]),"+f"(d[21]),"+f"(d[22]),"+f"(d[23]),"+f"(d[24]),"+f"(d[25]),"+f"(d[26]),"+f"(d[27]),"+f"(d[28]),"+f"(d[29]),"+f"(d[30]),"+f"(d[31]),"+f"(d[32]),"+f"(d[33]),"+f"(d[34]),"+f"(d[35]),"+f"(d[36]),"+f"(d[37]),"+f"(d[38]),"+f"(d[39]),"+f"(d[40]),"+f"(d[41]),"+f"(d[42]),"+f"(d[43]),"+f"(d[44]),"+f"(d[45]),"+f"(d[46]),"+f"(d[47]),"+f"(d[48]),"+f"(d[49]),"+f"(d[50]),"+f"(d[51]),"+f"(d[52]),"+f"(d[53]),"+f"(d[54]),"+f"(d[55]),"+f"(d[56]),"+f"(d[57]),"+f"(d[58]),"+f"(d[59]),"+f"(d[60]),"+f"(d[61]),"+f"(d[62]),"+f"(d[63]),"+f"(d[64]),"+f"(d[65]),"+f"(d[66]),"+f"(d[67]),"+f"(d[68]),"+f"(d[69]),"+f"(d[70]),"+f"(d[71])
    : "r"(al), "r"(ah), "r"(bl), "r"(bh), "n"(TB));
}
template<int TB> __device__ __forceinline__ void wgmma_ss_96_0(float (&d)[80], uint32_t al, uint32_t ah, uint32_t bl, uint32_t bh) {
  asm volatile("{\n.reg .b64 da, db;\nmov.b64 da, {%48, %49};\nmov.b64 db, {%50, %51};\n"
    "wgmma.mma_async.sync.aligned.m64n96k16.f32.bf16.bf16 {%0,%1,%2,%3,%4,%5,%6,%7,%8,%9,%10,%11,%12,%13,%14,%15,%16,%17,%18,%19,%20,%21,%22,%23,%24,%25,%26,%27,%28,%29,%30,%31,%32,%33,%34,%35,%36,%37,%38,%39,%40,%41,%42,%43,%44,%45,%46,%47}, da, db, 1, 1, 1, 1, %52;\n}\n"
    : "+f"(d[0]),"+f"(d[1]),"+f"(d[2]),"+f"(d[3]),"+f"(d[4]),"+f"(d[5]),"+f"(d[6]),"+f"(d[7]),"+f"(d[8]),"+f"(d[9]),"+f"(d[10]),"+f"(d[11]),"+f"(d[12]),"+f"(d[13]),"+f"(d[14]),"+f"(d[15]),"+f"(d[16]),"+f"(d[17]),"+f"(d[18]),"+f"(d[19]),"+f"(d[20]),"+f"(d[21]),"+f"(d[22]),"+f"(d[23]),"+f"(d[24]),"+f"(d[25]),"+f"(d[26]),"+f"(d[27]),"+f"(d[28]),"+f"(d[29]),"+f"(d[30]),"+f"(d[31]),"+f"(d[32]),"+f"(d[33]),"+f"(d[34]),"+f"(d[35]),"+f"(d[36]),"+f"(d[37]),"+f"(d[38]),"+f"(d[39]),"+f"(d[40]),"+f"(d[41]),"+f"(d[42]),"+f"(d[43]),"+f"(d[44]),"+f"(d[45]),"+f"(d[46]),"+f"(d[47])
    : "r"(al), "r"(ah), "r"(bl), "r"(bh), "n"(TB));
}
template<int TB> __device__ __forceinline__ void wgmma_ss_48_48(float (&d)[80], uint32_t al, uint32_t ah, uint32_t bl, uint32_t bh) {
  asm volatile("{\n.reg .b64 da, db;\nmov.b64 da, {%24, %25};\nmov.b64 db, {%26, %27};\n"
    "wgmma.mma_async.sync.aligned.m64n48k16.f32.bf16.bf16 {%0,%1,%2,%3,%4,%5,%6,%7,%8,%9,%10,%11,%12,%13,%14,%15,%16,%17,%18,%19,%20,%21,%22,%23}, da, db, 1, 1, 1, 1, %28;\n}\n"
    : "+f"(d[48]),"+f"(d[49]),"+f"(d[50]),"+f"(d[51]),"+f"(d[52]),"+f"(d[53]),"+f"(d[54]),"+f"(d[55]),"+f"(d[56]),"+f"(d[57]),"+f"(d[58]),"+f"(d[59]),"+f"(d[60]),"+f"(d[61]),"+f"(d[62]),"+f"(d[63]),"+f"(d[64]),"+f"(d[65]),"+f"(d[66]),"+f"(d[67]),"+f"(d[68]),"+f"(d[69]),"+f"(d[70]),"+f"(d[71])
    : "r"(al), "r"(ah), "r"(bl), "r"(bh), "n"(TB));
}
template<int TB> __device__ __forceinline__ void wgmma_rs_64(float (&d)[32], uint32_t a0, uint32_t a1, uint32_t a2, uint32_t a3, uint64_t db, int sd) {
  asm volatile("{\n.reg .pred p;\nsetp.ne.b32 p, %37, 0;\n"
    "wgmma.mma_async.sync.aligned.m64n64k16.f32.bf16.bf16 {%0,%1,%2,%3,%4,%5,%6,%7,%8,%9,%10,%11,%12,%13,%14,%15,%16,%17,%18,%19,%20,%21,%22,%23,%24,%25,%26,%27,%28,%29,%30,%31}, {%32,%33,%34,%35}, %36, p, 1, 1, %38;\n}\n"
    : "+f"(d[0]),"+f"(d[1]),"+f"(d[2]),"+f"(d[3]),"+f"(d[4]),"+f"(d[5]),"+f"(d[6]),"+f"(d[7]),"+f"(d[8]),"+f"(d[9]),"+f"(d[10]),"+f"(d[11]),"+f"(d[12]),"+f"(d[13]),"+f"(d[14]),"+f"(d[15]),"+f"(d[16]),"+f"(d[17]),"+f"(d[18]),"+f"(d[19]),"+f"(d[20]),"+f"(d[21]),"+f"(d[22]),"+f"(d[23]),"+f"(d[24]),"+f"(d[25]),"+f"(d[26]),"+f"(d[27]),"+f"(d[28]),"+f"(d[29]),"+f"(d[30]),"+f"(d[31])
    : "r"(a0), "r"(a1), "r"(a2), "r"(a3), "l"(db), "r"(sd), "n"(TB));
}
template<int TB> __device__ __forceinline__ void wgmma_rs_128(float (&d)[64], uint32_t a0, uint32_t a1, uint32_t a2, uint32_t a3, uint64_t db, int sd) {
  asm volatile("{\n.reg .pred p;\nsetp.ne.b32 p, %69, 0;\n"
    "wgmma.mma_async.sync.aligned.m64n128k16.f32.bf16.bf16 {%0,%1,%2,%3,%4,%5,%6,%7,%8,%9,%10,%11,%12,%13,%14,%15,%16,%17,%18,%19,%20,%21,%22,%23,%24,%25,%26,%27,%28,%29,%30,%31,%32,%33,%34,%35,%36,%37,%38,%39,%40,%41,%42,%43,%44,%45,%46,%47,%48,%49,%50,%51,%52,%53,%54,%55,%56,%57,%58,%59,%60,%61,%62,%63}, {%64,%65,%66,%67}, %68, p, 1, 1, %70;\n}\n"
    : "+f"(d[0]),"+f"(d[1]),"+f"(d[2]),"+f"(d[3]),"+f"(d[4]),"+f"(d[5]),"+f"(d[6]),"+f"(d[7]),"+f"(d[8]),"+f"(d[9]),"+f"(d[10]),"+f"(d[11]),"+f"(d[12]),"+f"(d[13]),"+f"(d[14]),"+f"(d[15]),"+f"(d[16]),"+f"(d[17]),"+f"(d[18]),"+f"(d[19]),"+f"(d[20]),"+f"(d[21]),"+f"(d[22]),"+f"(d[23]),"+f"(d[24]),"+f"(d[25]),"+f"(d[26]),"+f"(d[27]),"+f"(d[28]),"+f"(d[29]),"+f"(d[30]),"+f"(d[31]),"+f"(d[32]),"+f"(d[33]),"+f"(d[34]),"+f"(d[35]),"+f"(d[36]),"+f"(d[37]),"+f"(d[38]),"+f"(d[39]),"+f"(d[40]),"+f"(d[41]),"+f"(d[42]),"+f"(d[43]),"+f"(d[44]),"+f"(d[45]),"+f"(d[46]),"+f"(d[47]),"+f"(d[48]),"+f"(d[49]),"+f"(d[50]),"+f"(d[51]),"+f"(d[52]),"+f"(d[53]),"+f"(d[54]),"+f"(d[55]),"+f"(d[56]),"+f"(d[57]),"+f"(d[58]),"+f"(d[59]),"+f"(d[60]),"+f"(d[61]),"+f"(d[62]),"+f"(d[63])
    : "r"(a0), "r"(a1), "r"(a2), "r"(a3), "l"(db), "r"(sd), "n"(TB));
}
template<int TB> __device__ __forceinline__ void wgmma_rs_144(float (&d)[72], uint32_t a0, uint32_t a1, uint32_t a2, uint32_t a3, uint64_t db, int sd) {
  asm volatile("{\n.reg .pred p;\nsetp.ne.b32 p, %77, 0;\n"
    "wgmma.mma_async.sync.aligned.m64n144k16.f32.bf16.bf16 {%0,%1,%2,%3,%4,%5,%6,%7,%8,%9,%10,%11,%12,%13,%14,%15,%16,%17,%18,%19,%20,%21,%22,%23,%24,%25,%26,%27,%28,%29,%30,%31,%32,%33,%34,%35,%36,%37,%38,%39,%40,%41,%42,%43,%44,%45,%46,%47,%48,%49,%50,%51,%52,%53,%54,%55,%56,%57,%58,%59,%60,%61,%62,%63,%64,%65,%66,%67,%68,%69,%70,%71}, {%72,%73,%74,%75}, %76, p, 1, 1, %78;\n}\n"
    : "+f"(d[0]),"+f"(d[1]),"+f"(d[2]),"+f"(d[3]),"+f"(d[4]),"+f"(d[5]),"+f"(d[6]),"+f"(d[7]),"+f"(d[8]),"+f"(d[9]),"+f"(d[10]),"+f"(d[11]),"+f"(d[12]),"+f"(d[13]),"+f"(d[14]),"+f"(d[15]),"+f"(d[16]),"+f"(d[17]),"+f"(d[18]),"+f"(d[19]),"+f"(d[20]),"+f"(d[21]),"+f"(d[22]),"+f"(d[23]),"+f"(d[24]),"+f"(d[25]),"+f"(d[26]),"+f"(d[27]),"+f"(d[28]),"+f"(d[29]),"+f"(d[30]),"+f"(d[31]),"+f"(d[32]),"+f"(d[33]),"+f"(d[34]),"+f"(d[35]),"+f"(d[36]),"+f"(d[37]),"+f"(d[38]),"+f"(d[39]),"+f"(d[40]),"+f"(d[41]),"+f"(d[42]),"+f"(d[43]),"+f"(d[44]),"+f"(d[45]),"+f"(d[46]),"+f"(d[47]),"+f"(d[48]),"+f"(d[49]),"+f"(d[50]),"+f"(d[51]),"+f"(d[52]),"+f"(d[53]),"+f"(d[54]),"+f"(d[55]),"+f"(d[56]),"+f"(d[57]),"+f"(d[58]),"+f"(d[59]),"+f"(d[60]),"+f"(d[61]),"+f"(d[62]),"+f"(d[63]),"+f"(d[64]),"+f"(d[65]),"+f"(d[66]),"+f"(d[67]),"+f"(d[68]),"+f"(d[69]),"+f"(d[70]),"+f"(d[71])
    : "r"(a0), "r"(a1), "r"(a2), "r"(a3), "l"(db), "r"(sd), "n"(TB));
}
template<int N,int OFF,int TB> __device__ __forceinline__ void wgmma_ss(float (&d)[80], uint32_t al, uint32_t ah, uint32_t bl, uint32_t bh) {
  if constexpr (N==160) wgmma_ss_160_0<TB>(d, al, ah, bl, bh);
  else if constexpr (N==144) wgmma_ss_144_0<TB>(d, al, ah, bl, bh);
  else if constexpr (N==96) wgmma_ss_96_0<TB>(d, al, ah, bl, bh);
  else if constexpr (N==48) wgmma_ss_48_48<TB>(d, al, ah, bl, bh);
}

__device__ __forceinline__ void dft3(float2& a, float2& b, float2& c) {
  const float s = 0.86602540378443864676f;
  float2 t = make_float2(b.x + c.x, b.y + c.y), d = make_float2(b.x - c.x, b.y - c.y);
  float2 m = make_float2(fmaf(-0.5f, t.x, a.x), fmaf(-0.5f, t.y, a.y));
  a = make_float2(a.x + t.x, a.y + t.y);
  b = make_float2(fmaf(s, d.y, m.x), fmaf(-s, d.x, m.y));
  c = make_float2(fmaf(-s, d.y, m.x), fmaf(s, d.x, m.y));
}
__device__ __forceinline__ void dft9(float2 (&x)[9]) {
  const float2 w1 = make_float2(0.76604444311897803520f, -0.64278760968653932632f);
  const float2 w2 = make_float2(0.17364817766693034885f, -0.98480775301220805937f);
  const float2 w4 = make_float2(-0.93969262078590838405f, -0.34202014332566873304f);
  dft3(x[0], x[3], x[6]); dft3(x[1], x[4], x[7]); dft3(x[2], x[5], x[8]);
  x[4] = cmul(x[4], w1); x[7] = cmul(x[7], w2); x[5] = cmul(x[5], w2); x[8] = cmul(x[8], w4);
  dft3(x[0], x[1], x[2]); dft3(x[3], x[4], x[5]); dft3(x[6], x[7], x[8]);
  float2 t;
  t = x[1]; x[1] = x[3]; x[3] = t;
  t = x[2]; x[2] = x[6]; x[6] = t;
  t = x[5]; x[5] = x[7]; x[7] = t;
}

__device__ __forceinline__ void mod_issue(const Maps& maps, int cta, uint32_t stg, uint32_t mbar) {
  mbar_expect(mbar, 36864);
#pragma unroll 1
  for (int i = 0; i < 3; i++) tma2d(stg + i * 12288, &maps.wm, 32 * cta, 192 * i, mbar);
}
__device__ __forceinline__ void phase_mod(const Params& p, int cta, int t128, float* red  , uint32_t stg, uint32_t mbar) {
  const int q = t128 & 3, rg = t128 >> 2;
  float* sil = red + 128;
  {
    float cv[5];
#pragma unroll
    for (int i = 0; i < 5; i++) cv[i] = (i < 4 || t128 < 64) ? __bfloat162float(p.c[t128 + 128 * i]) : 0.f;
#pragma unroll
    for (int i = 0; i < 5; i++) if (i < 4 || t128 < 64) sil[t128 + 128 * i] = rbf(__fdividef(cv[i], 1.0f + __expf(-cv[i])));
  }
  bar_sync(4, 128);
  mbar_wait(mbar, 0);
  float acc[8];
#pragma unroll
  for (int e = 0; e < 8; e++) acc[e] = 0.f;
#pragma unroll 2
  for (int i = 0; i < 18; i++) {
    const float sc = sil[rg + 32 * i];
    uint4 wv;
    asm volatile("ld.shared.v4.b32 {%0,%1,%2,%3}, [%4];" : "=r"(wv.x), "=r"(wv.y), "=r"(wv.z), "=r"(wv.w) : "r"(stg + (t128 + 128 * i) * 16));
    acc[0] = fmaf(sc, bf_lo(wv.x), acc[0]); acc[1] = fmaf(sc, bf_hi(wv.x), acc[1]);
    acc[2] = fmaf(sc, bf_lo(wv.y), acc[2]); acc[3] = fmaf(sc, bf_hi(wv.y), acc[3]);
    acc[4] = fmaf(sc, bf_lo(wv.z), acc[4]); acc[5] = fmaf(sc, bf_hi(wv.z), acc[5]);
    acc[6] = fmaf(sc, bf_lo(wv.w), acc[6]); acc[7] = fmaf(sc, bf_hi(wv.w), acc[7]);
  }
#pragma unroll 1
  for (int o = 4; o < 32; o <<= 1) {
#pragma unroll
    for (int e = 0; e < 8; e++) acc[e] += __shfl_xor_sync(0xffffffffu, acc[e], o);
  }
  if ((t128 & 31) < 4) {
    *reinterpret_cast<float4*>(red + (t128 >> 5) * 32 + 8 * q) = make_float4(acc[0], acc[1], acc[2], acc[3]);
    *reinterpret_cast<float4*>(red + (t128 >> 5) * 32 + 8 * q + 4) = make_float4(acc[4], acc[5], acc[6], acc[7]);
  }
  bar_sync(4, 128);
  if (t128 < 16) {
    const int e = 2 * t128;
    g_mod[16 * cta + t128] = nz(pack_bf16(red[e] + red[32 + e] + red[64 + e] + red[96 + e], red[e + 1] + red[33 + e] + red[65 + e] + red[97 + e]));
  }
  if (t128 < 32) {
    __syncwarp();
    if (t128 == 0) { signal_rlx(&g_cnt[cta < 36 ? C_MODA : C_MODB]); TS(25); }
  }
}

__device__ __forceinline__ void phase_wt(const Params& p, int c, int t128, uint8_t* smem) {
  uint16_t* T = reinterpret_cast<uint16_t*>(smem + FS_Y);
  const int k1 = c & 31, jp = c >> 5, par = k1 & 1;
  const int w = t128 >> 5, l = t128 & 31;
#pragma unroll 1
  for (int rr = 0; rr < 8; rr++) {
    const int r = 8 * w + rr;
    const int ks = k1 + 32 * (8 * jp + rr) + 1024 * (w & 1);
    const uint32_t* src = reinterpret_cast<const uint32_t*>((w >> 1) ? p.wi : p.wr) + (((size_t)ks * DF_ - par) >> 1) + l;
    const uint32_t dst = smem_u32(T) + r * 584 + l * 4;
#pragma unroll
    for (int it = 0; it < 5; it++)
      if (it < 4 || l < 17) asm volatile("cp.async.ca.shared.global [%0], [%1], 4;" ::"r"(dst + it * 128), "l"(src + it * 32) : "memory");
  }
  uint32_t sym = 0;
  if (t128 < 32) {
    int r = t128 & 15, pc = (t128 >> 4) ? 288 : 0;
    int ks = k1 + 32 * (8 * jp + (r & 7)) + 1024 * (r >> 3);
    int km = (S_ - ks) & (S_ - 1);
    float ar = __bfloat162float(p.wr[ks * DF_ + pc]), ai = __bfloat162float(p.wi[ks * DF_ + pc]);
    float br = __bfloat162float(p.wr[km * DF_ + pc]), bi = __bfloat162float(p.wi[km * DF_ + pc]);
    sym = pack_bf16(0.5f * (ar + br), 0.5f * (ai - bi));
  }
  asm volatile("cp.async.wait_all;" ::: "memory");
  bar_sync(4, 128);
  if (t128 < 32) {
    int r = t128 & 15, pc = ((t128 >> 4) ? 288 : 0) + par;
    T[r * 292 + pc] = (uint16_t)(sym & 0xffff);
    T[(16 + r) * 292 + pc] = (uint16_t)(sym >> 16);
  }
  bar_sync(4, 128);
  uint4* dstw = g_WT + jp * 128 + 32 * (k1 >> 3) + 4 * (k1 & 7) + (t128 & 3);
  const uint16_t* Tt = T + (t128 & 3) * 292 + par;
#pragma unroll 1
  for (int pp = t128 >> 2; pp < DF_; pp += 32) {
    uint4 o;
    o.x = (uint32_t)Tt[pp] | ((uint32_t)Tt[16 * 292 + pp] << 16);
    o.y = (uint32_t)Tt[8 * 292 + pp] | ((uint32_t)Tt[24 * 292 + pp] << 16);
    o.z = (uint32_t)Tt[4 * 292 + pp] | ((uint32_t)Tt[20 * 292 + pp] << 16);
    o.w = (uint32_t)Tt[12 * 292 + pp] | ((uint32_t)Tt[28 * 292 + pp] << 16);
    dstw[pp * 512] = make_uint4(nz(o.x), nz(o.y), nz(o.z), nz(o.w));
  }
  }

__device__ __forceinline__ void ln_stats2(const float (&a)[18], const float (&b)[18], float& ma, float& ra, float& mb, float& rb) {
  float v[4] = {0.f, 0.f, 0.f, 0.f};
#pragma unroll
  for (int i = 0; i < 18; i++) { v[0] += a[i]; v[1] = fmaf(a[i], a[i], v[1]); v[2] += b[i]; v[3] = fmaf(b[i], b[i], v[3]); }
#pragma unroll 1
  for (int o = 16; o; o >>= 1) {
#pragma unroll
    for (int e = 0; e < 4; e++) v[e] += __shfl_xor_sync(0xffffffffu, v[e], o);
  }
  ma = v[0] * (1.0f / D_); mb = v[2] * (1.0f / D_);
  ra = rsqrtf(fmaxf(fmaf(-ma, ma, v[1] * (1.0f / D_)), 0.f) + 1e-5f);
  rb = rsqrtf(fmaxf(fmaf(-mb, mb, v[3] * (1.0f / D_)), 0.f) + 1e-5f);
}

__device__ __forceinline__ void fetch_mod(uint32_t* smod, int w0, int nw4, int tid) {
  int it = 0;
#pragma unroll 1
  while (true) {
    uint32_t bad = 0;
    if (tid < nw4) {
      const uint4 v = ld_rlx4(g_mod + w0 + 4 * tid);
      bad = !ok4(v);
      *reinterpret_cast<uint4*>(smod + 4 * tid) = v;
    }
    uint32_t any;
    asm volatile("{\n.reg .pred p, q;\nsetp.ne.u32 p, %1, 0;\nbarrier.cta.red.or.pred q, 1, 256, p;\nselp.u32 %0, 1, 0, q;\n}" : "=r"(any) : "r"(bad) : "memory");
    if (!any) break;
    spin_guard(it);
  }
}

__device__ __forceinline__ void phase1(const Maps& maps, int c, int tid, uint8_t* smem, const uint32_t (&xr)[18], uint32_t* smod) {
  const int w = tid >> 5, l = tid & 31;
  TC(16);
  float a[18], b[18];
#pragma unroll
  for (int i = 0; i < 9; i++) { a[2 * i] = bf_lo(xr[i]); a[2 * i + 1] = bf_hi(xr[i]); b[2 * i] = bf_lo(xr[9 + i]); b[2 * i + 1] = bf_hi(xr[9 + i]); }
  float ma, ra, mb, rb;
  TC(17);
  ln_stats2(a, b, ma, ra, mb, rb);
  TC(18);
  if (c >= 36) asm volatile("bar.arrive 7, %0;" ::"n"(NTHR) : "memory");
  float4 tw[8];
#pragma unroll
  for (int i = 0; i < 8; i++) tw[i] = __ldg(reinterpret_cast<const float4*>(T_TW576) + l * 8 + i);
  uint4 af[4];
#pragma unroll
  for (int kk = 0; kk < 4; kk++) af[kk] = __ldg(reinterpret_cast<const uint4*>(T_F64) + ((tid >> 7) * 4 + kk) * 128 + (tid & 127));
  if (tid == 0) TS(2);
  TC(19);
  if (tid == 0) wait_hint(&g_cnt[C_MODA], 36);
  TC(20);
  bar_sync(1, 256);
  fetch_mod(smod, 0, 144, tid);
  uint32_t sh[9], sc[9];
#pragma unroll
  for (int i = 0; i < 9; i++) { sh[i] = smod[32 * i + l]; sc[i] = smod[288 + 32 * i + l]; }
  if (tid == 0) TS(3);
  TC(21);
  asm volatile("bar.arrive 6, %0;" ::"n"(NTHR) : "memory");
  const uint32_t sB = smem_u32(smem + FS_B);
#pragma unroll
  for (int i = 0; i < 9; i++) {
    const float c0 = rbf(1.0f + bf_lo(sc[i])), c1 = rbf(1.0f + bf_hi(sc[i])), s0 = bf_lo(sh[i]), s1 = bf_hi(sh[i]);
    a[2 * i] = fmaf((a[2 * i] - ma) * ra, c0, s0); a[2 * i + 1] = fmaf((a[2 * i + 1] - ma) * ra, c1, s1);
    b[2 * i] = fmaf((b[2 * i] - mb) * rb, c0, s0); b[2 * i + 1] = fmaf((b[2 * i + 1] - mb) * rb, c1, s1);
  }
#pragma unroll
  for (int e = 0; e < 2; e++) {
    float2 z[9];
#pragma unroll
    for (int i = 0; i < 9; i++) z[i] = make_float2(a[2 * i + e], b[2 * i + e]);
    dft9(z);
#pragma unroll
    for (int k1 = 1; k1 < 9; k1++) {
      int q = e * 8 + k1 - 1;
      float2 t = (q & 1) ? make_float2(tw[q >> 1].z, tw[q >> 1].w) : make_float2(tw[q >> 1].x, tw[q >> 1].y);
      z[k1] = cmul(z[k1], t);
    }
    if (e == 0) {
#pragma unroll
      for (int k1 = 0; k1 < 9; k1++) { a[2 * k1] = z[k1].x; b[2 * k1] = z[k1].y; }
    } else {
#pragma unroll
      for (int k1 = 0; k1 < 9; k1++) { a[2 * k1 + 1] = z[k1].x; b[2 * k1 + 1] = z[k1].y; }
    }
  }
  TC(22);
#pragma unroll
  for (int k1 = 0; k1 < 9; k1++) {
    int n = 16 * k1 + 8 * (w & 1) + 2 * (w >> 1);
    uint32_t a0 = sB + n * 128 + (((l >> 2) ^ (n & 7)) << 4) + (l & 3) * 4;
    uint32_t a1 = sB + (n + 1) * 128 + (((l >> 2) ^ ((n + 1) & 7)) << 4) + (l & 3) * 4;
    asm volatile("st.shared.b32 [%0], %1;" ::"r"(a0), "r"(pack_bf16(a[2 * k1], a[2 * k1 + 1])) : "memory");
    asm volatile("st.shared.b32 [%0], %1;" ::"r"(a1), "r"(pack_bf16(b[2 * k1], b[2 * k1 + 1])) : "memory");
  }
  TC(23);
  fence_async_smem();
  bar_sync(1, 256);
  TC(24);
  float acc[72];
  reg_fence(acc);
  wg_fence();
#pragma unroll
  for (int kk = 0; kk < 4; kk++) wgmma_rs_144<0>(acc, af[kk].x, af[kk].y, af[kk].z, af[kk].w, mkdesc(sB + kk * 32, 16, 1024, 1), kk);
  wg_commit();
  wg_wait<0>();
  reg_fence(acc);
  TC(25);
  const int ww = w & 3, g = l >> 2, t = l & 3, m = tid >> 7;
  const int k2 = 32 * m + 8 * ww + g;
  const uint32_t cj = m ? 0x80000000u : 0u;
  const uint32_t stg = smem_u32(smem + STAGE);
  const uint32_t zp = stg + (m ? 865 - 9 * k2 : 9 * k2) * 32 + 8 * t;
  const int zstep = m ? -32 : 32;
#pragma unroll
  for (int k1 = 0; k1 < 9; k1++) {
    uint32_t o0 = pack_bf16(acc[8 * k1 + 0] - acc[8 * k1 + 3], acc[8 * k1 + 1] + acc[8 * k1 + 2]);
    uint32_t o1 = pack_bf16(acc[8 * k1 + 4] - acc[8 * k1 + 7], acc[8 * k1 + 5] + acc[8 * k1 + 6]);
    asm volatile("st.shared.v2.b32 [%0], {%1,%2};" ::"r"(zp + k1 * zstep), "r"(nz(o0 ^ cj)), "r"(nz(o1 ^ cj)) : "memory");
    if (k1 == 0 && (k2 & 31) == 0)
      asm volatile("st.shared.v2.b32 [%0], {%1,%2};" ::"r"(stg + (m ? 288 : DF_) * 32 + 8 * t), "r"(nz(o0 ^ cj ^ 0x80000000u)), "r"(nz(o1 ^ cj ^ 0x80000000u)) : "memory");
  }
  TC(26);
  fence_async_smem();
  bar_sync(1, 256);
  if (tid == 0) {
#pragma unroll 1
    for (int i = 0; i < 3; i++) tma_st2d(&maps.z1, stg + i * (196 * 32), 8 * c, 196 * i);
    bulk_commit_wait_read();
    signal_rlx(&g_cnt[C_Z1]);
    TS(4);
  }
  TC(27);
}

__device__ __forceinline__ void phase2(const Maps& maps, int task, int wg, int t128, uint8_t* smem, uint32_t gbar) {
  const int w = t128 >> 5, l = t128 & 31, g = l >> 2, t = l & 3;
  const uint32_t sD = smem_u32(smem + FS_B + wg * 8192), sG = smem_u32(smem + FS_G);
  TD(0);
  uint4 af[2];
#pragma unroll
  for (int kk = 0; kk < 2; kk++) af[kk] = __ldg(reinterpret_cast<const uint4*>(T_F32) + kk * 128 + t128);
  float4 twa[4], twb[4], th[4];
#pragma unroll
  for (int i = 0; i < 4; i++) {
    twa[i] = __ldg(reinterpret_cast<const float4*>(T_TWA) + i * 128 + t128);
    th[i] = __ldg(reinterpret_cast<const float4*>(T_TH) + i * 128 + t128);
  }
  TD(1);
  if (t128 == 0) wait_hint(&g_cnt[C_Z1], 128);
  TD(2);
  bar_sync(2 + wg, 128);
  TD(3);
  uint4 wt[4];
  {
    uint4 v[4];
    const uint4* zsrc = reinterpret_cast<const uint4*>(g_Z1);
    int it = 0; bool ok;
#pragma unroll 1
    do {
      ok = true;
#pragma unroll
      for (int i = 0; i < 4; i++) v[i] = ld_rlx4(zsrc + (size_t)((i >> 1) ? DF_ + task : task) * 256 + t128 + 128 * (i & 1));
#pragma unroll
      for (int i = 0; i < 4; i++) ok = ok & ok4(v[i]);
      if (!ok) spin_guard(it);
    } while (!ok);
    if (t128 == 0 && wg == 0) TS(8);
    TD(4);
#pragma unroll
    for (int i = 0; i < 4; i++) wt[i] = ld_rlx4(g_WT + task * 512 + i * 128 + t128);
#pragma unroll
    for (int i = 0; i < 4; i++) {
      const int ch = t128 + 128 * (i & 1), row = ch >> 3, cc = ch & 7;
      uint32_t a = sD + (i >> 1) * 4096 + row * 128 + ((cc ^ (row & 7)) << 4);
      asm volatile("st.shared.v4.b32 [%0], {%1,%2,%3,%4};" ::"r"(a), "r"(v[i].x), "r"(v[i].y), "r"(v[i].z), "r"(v[i].w) : "memory");
    }
  }
  TD(5);
  fence_async_smem();
  mbar_wait(gbar, 0);
  bar_sync(2 + wg, 128);
  TD(6);
  float acc[64];
  uint32_t A[16];
  reg_fence(acc);
  wg_fence();
#pragma unroll
  for (int kk = 0; kk < 2; kk++) wgmma_rs_128<1>(acc, af[kk].x, af[kk].y, af[kk].z, af[kk].w, mkdesc(sD + kk * 2048, 4096, 1024, 1), kk);
  wg_commit();
  wg_wait<0>();
  reg_fence(acc);
  TD(7);
#pragma unroll
  for (int j = 0; j < 8; j++) {
    float2 tw = (j & 1) ? make_float2(twa[j >> 1].z, twa[j >> 1].w) : make_float2(twa[j >> 1].x, twa[j >> 1].y);
#pragma unroll
    for (int ln = 0; ln < 2; ln++) {
      const float* q = &acc[(ln * 8 + j) * 4];
      float2 z = cmul(make_float2(q[0] - q[3], q[1] + q[2]), tw);
      A[(j >> 1) * 4 + (j & 1) * 2 + ln] = pack_bf16(z.x, z.y);
    }
  }
  TD(8);
#pragma unroll
  for (int i = 0; i < 4; i++) { uint4 v = ld_rlx4(reinterpret_cast<const float4*>(T_TWB) + i * 128 + t128); twb[i] = make_float4(__uint_as_float(v.x), __uint_as_float(v.y), __uint_as_float(v.z), __uint_as_float(v.w)); }
  float ac2[32];
  reg_fence(ac2);
  wg_fence();
#pragma unroll
  for (int kk = 0; kk < 4; kk++) wgmma_rs_64<0>(ac2, A[4 * kk], A[4 * kk + 1], A[4 * kk + 2], A[4 * kk + 3], mkdesc(sG + kk * 32, 16, 1024, 1), kk);
  wg_commit();
  wg_wait<0>();
  reg_fence(ac2);
  TD(9);
  {
    int it = 0;
    while (!(ok4(wt[0]) && ok4(wt[1]) && ok4(wt[2]) && ok4(wt[3]))) {
#pragma unroll
      for (int i = 0; i < 4; i++) wt[i] = ld_rlx4(g_WT + task * 512 + i * 128 + t128);
      spin_guard(it);
    }
  }
  TD(10);
  const float nrm = 1.0f / (1024.0f * 576.0f);
#pragma unroll
  for (int j = 0; j < 8; j++) {
    uint32_t u0 = (j & 1) ? wt[j >> 1].z : wt[j >> 1].x, u1 = (j & 1) ? wt[j >> 1].w : wt[j >> 1].y;
    float sn = (j & 1) ? th[j >> 1].z : th[j >> 1].x, cs = (j & 1) ? th[j >> 1].w : th[j >> 1].y;
    float2 P = make_float2((bf_lo(u0) + bf_lo(u1)) * (0.5f * nrm), (bf_hi(u0) + bf_hi(u1)) * (0.5f * nrm));
    float2 Q = make_float2((bf_lo(u0) - bf_lo(u1)) * (0.5f * nrm), (bf_hi(u0) - bf_hi(u1)) * (0.5f * nrm));
    float2 a1 = make_float2(fmaf(-Q.x, sn, P.x), fmaf(-Q.y, sn, P.y));
    float2 a2 = make_float2(fmaf(Q.x, sn, P.x), fmaf(Q.y, sn, P.y));
    float2 be = make_float2(-Q.y * cs, Q.x * cs);
    float2 Z = make_float2(ac2[4 * j], ac2[4 * j + 1]), U = make_float2(ac2[4 * j + 2], ac2[4 * j + 3]);
    float2 zn = cmul(a1, Z), t1 = cmul(be, U), un = cmul(a2, U), t2 = cmul(be, Z);
    A[(j >> 1) * 4 + (j & 1) * 2 + 0] = pack_bf16(zn.x + t1.x, -(zn.y + t1.y));
    A[(j >> 1) * 4 + (j & 1) * 2 + 1] = pack_bf16(un.x - t2.x, -(un.y - t2.y));
  }
  TD(11);
  reg_fence(ac2);
  wg_fence();
#pragma unroll
  for (int kk = 0; kk < 4; kk++) wgmma_rs_64<0>(ac2, A[4 * kk], A[4 * kk + 1], A[4 * kk + 2], A[4 * kk + 3], mkdesc(sG + 8192 + kk * 32, 16, 1024, 1), kk);
  wg_commit();
  wg_wait<0>();
  reg_fence(ac2);
#pragma unroll
  for (int j = 0; j < 8; j++) {
    float2 tw = (j & 1) ? make_float2(twb[j >> 1].z, twb[j >> 1].w) : make_float2(twb[j >> 1].x, twb[j >> 1].y);
    float2 za = cmul(make_float2(ac2[4 * j], ac2[4 * j + 1]), tw), zb = cmul(make_float2(ac2[4 * j + 2], ac2[4 * j + 3]), tw);
    A[j] = pack_bf16(za.x, za.y); A[8 + j] = pack_bf16(zb.x, zb.y);
  }
  TD(12);
  {
    const int mi = l >> 3, r = l & 7;
#pragma unroll
    for (int ln = 0; ln < 2; ln++)
#pragma unroll
      for (int jq = 0; jq < 2; jq++) {
        uint32_t a = sD + ln * 4096 + (8 * w + r) * 128 + (((4 * jq + mi) ^ r) << 4);
        stmatrix4(a, A[ln * 8 + 4 * jq], A[ln * 8 + 4 * jq + 1], A[ln * 8 + 4 * jq + 2], A[ln * 8 + 4 * jq + 3]);
      }
  }
  fence_async_smem();
  bar_sync(2 + wg, 128);
  TD(13);
  reg_fence(acc);
  wg_fence();
#pragma unroll
  for (int kk = 0; kk < 2; kk++) wgmma_rs_128<1>(acc, af[kk].x, af[kk].y, af[kk].z, af[kk].w, mkdesc(sD + kk * 2048, 4096, 1024, 1), kk);
  wg_commit();
  wg_wait<0>();
  reg_fence(acc);
  TD(14);
  bar_sync(2 + wg, 128);
  const int nl = (task != 0 && task != 288) ? 2 : 1;
#pragma unroll
  for (int ln = 0; ln < 2; ln++) {
    const int kd = ln ? D_ - task : task, k2 = kd / 9;
    const uint32_t sg = ln ? 0x80000000u : 0u;
    uint32_t o[8];
#pragma unroll
    for (int j = 0; j < 8; j++) { const float* q = &acc[(8 * ln + j) * 4]; o[j] = nz(pack_bf16(q[0] - q[3], q[1] + q[2]) ^ sg); }
    const uint32_t a = sD + ln * 4096 + (8 * w + g) * 128 + ((t ^ ((k2 >> 1) & 1)) << 4);
    asm volatile("st.shared.v4.b32 [%0], {%1,%2,%3,%4};" ::"r"(a), "r"(o[0]), "r"(o[1]), "r"(o[2]), "r"(o[3]) : "memory");
    asm volatile("st.shared.v4.b32 [%0], {%1,%2,%3,%4};" ::"r"(a + 64), "r"(o[4]), "r"(o[5]), "r"(o[6]), "r"(o[7]) : "memory");
  }
  TD(15);
  fence_async_smem();
  bar_sync(2 + wg, 128);
  TD(16);
  if (t128 == 0) {
#pragma unroll 1
    for (int ln = 0; ln < nl; ln++) {
      const int kd = ln ? D_ - task : task, k2 = kd / 9, k1 = kd - 9 * k2;
      tma_st3d(&maps.z2, sD + ln * 4096, 0, 128 * (k1 >> 1) + 2 * k2 + ((k1 & 1) ^ ((k2 >> 2) & 1)), 0);
    }
    bulk_commit_wait_read();
    signal_rlx(&g_cnt[C_Z2]);
    if (wg == 0) TS(9);
  }
  TD(17);
}

__device__ __forceinline__ void phase3(const Params& p, int c, int tid, uint8_t* smem, uint32_t zbar, uint32_t* smod, uint32_t (&xr)[18]) {
  const int w = tid >> 5, l = tid & 31;
  const uint32_t sB = smem_u32(smem + FS_B), sY = smem_u32(smem + FS_Y);
  const int m = tid >> 7, ww = w & 3, g = l >> 2, t = l & 3;
  const int n2 = 32 * m + 8 * ww + g;
  TC(0);
  uint4 af[4];
#pragma unroll
  for (int kk = 0; kk < 4; kk++) af[kk] = __ldg(reinterpret_cast<const uint4*>(T_F64) + (m * 4 + kk) * 128 + (tid & 127));
  float4 tw[4];
#pragma unroll
  for (int i = 0; i < 4; i++) tw[i] = __ldg(reinterpret_cast<const float4*>(T_TW576) + n2 * 4 + i);
#pragma unroll
  for (int i = 0; i < 9; i++) {
    xr[i] = __ldg(reinterpret_cast<const uint32_t*>(p.x) + (size_t)(16 * c + 2 * w) * 288 + 32 * i + l);
    xr[9 + i] = __ldg(reinterpret_cast<const uint32_t*>(p.x) + (size_t)(16 * c + 2 * w + 1) * 288 + 32 * i + l);
  }
  bar_sync(1, 256);
  fetch_mod(smod, 576, 216, tid);
  const uint32_t* zsrc = g_Z2 + (size_t)c * 5120;
  {
    int it = 0;
    if (tid == 0) wait_hint(&g_cnt[C_Z2], DF_);
    TC(2);
#pragma unroll 1
    while (true) {
      if (tid == 0) { mbar_expect(zbar, 20480); bulk_ld(sB, zsrc, 20480, zbar); }
      mbar_wait(zbar, it & 1);
      uint32_t bad = 0;
#pragma unroll
      for (int i = 0; i < 5; i++) {
        if (i < 4 || tid < 128) {
          uint4 v;
          asm volatile("ld.shared.v4.b32 {%0,%1,%2,%3}, [%4];" : "=r"(v.x), "=r"(v.y), "=r"(v.z), "=r"(v.w) : "r"(sB + (i < 4 ? tid + 256 * i : 1024 + 4 * (tid >> 1) + 2 * ((tid >> 3) & 1) + (tid & 1)) * 16) : "memory");
          bad |= !ok4(v);
        }
      }
      uint32_t any;
      asm volatile("{\n.reg .pred p, q;\nsetp.ne.u32 p, %1, 0;\nbarrier.cta.red.or.pred q, 1, 256, p;\nselp.u32 %0, 1, 0, q;\n}" : "=r"(any) : "r"(bad) : "memory");
      if (!any) break;
      spin_guard(it);
    }
    if (tid == 0) TS(11);
    if (PFMODE != 0) asm volatile("bar.arrive 10, 288;" ::: "memory");
    TC(3);
  }
  TC(4);
  float acc[72];
  reg_fence(acc);
  wg_fence();
#pragma unroll
  for (int kk = 0; kk < 4; kk++) wgmma_rs_144<1>(acc, af[kk].x, af[kk].y, af[kk].z, af[kk].w, mkdesc(sB + kk * 1024, 4096, 512, 2), kk);
  wg_commit();
  TC(1);
  TC(5);
  wg_wait<0>();
  reg_fence(acc);
  TC(6);
#pragma unroll
  for (int h = 0; h < 2; h++) {
    float2 z[9];
#pragma unroll
    for (int k1 = 0; k1 < 9; k1++) {
      const float* q = &acc[(2 * k1 + h) * 4];
      z[k1] = make_float2(q[0] - q[3], q[1] + q[2]);
      if (k1 > 0) {
        int qi = k1 - 1;
        float2 tt = (qi & 1) ? make_float2(tw[qi >> 1].z, tw[qi >> 1].w) : make_float2(tw[qi >> 1].x, tw[qi >> 1].y);
        z[k1] = cmul(z[k1], tt);
      }
    }
    dft9(z);
#pragma unroll
    for (int n1 = 0; n1 < 9; n1++) {
      uint32_t a = sY + ((4 * h + t) * 584 + 64 * n1 + n2) * 4;
      asm volatile("st.shared.b32 [%0], %1;" ::"r"(a), "r"(pack_bf16(z[n1].x, -z[n1].y)) : "memory");
    }
  }
  TC(7);
  bar_sync(1, 256);
  TC(8);
  float a[18], b[18];
#pragma unroll
  for (int i = 0; i < 9; i++) {
    uint32_t y0, y1;
    asm volatile("ld.shared.v2.b32 {%0,%1}, [%2];" : "=r"(y0), "=r"(y1) : "r"(sY + (w * 584 + 64 * i + 2 * l) * 4));
    const uint32_t gai = smod[32 * i + l];
    const uint32_t xa = hadd2(xr[i], hmul2(gai, __byte_perm(y0, y1, 0x5410)));
    const uint32_t xb = hadd2(xr[9 + i], hmul2(gai, __byte_perm(y0, y1, 0x7632)));
    xr[i] = xa; xr[9 + i] = xb;
    a[2 * i] = bf_lo(xa); a[2 * i + 1] = bf_hi(xa); b[2 * i] = bf_lo(xb); b[2 * i + 1] = bf_hi(xb);
  }
  {
    uint32_t* xd = g_x1 + (size_t)(16 * c + 2 * w) * 288 + l;
#pragma unroll
    for (int i = 0; i < 9; i++) { xd[32 * i] = xr[i]; xd[288 + 32 * i] = xr[9 + i]; }
  }
  float ma, ra, mb, rb;
  TC(9);
  ln_stats2(a, b, ma, ra, mb, rb);
  TC(10);
#pragma unroll
  for (int i = 0; i < 9; i++) {
    const uint32_t c2 = hadd2(smod[576 + 32 * i + l], 0x3f803f80u), sbi = smod[288 + 32 * i + l];
    const uint32_t ha = hadd2(hmul2(pack_bf16((a[2 * i] - ma) * ra, (a[2 * i + 1] - ma) * ra), c2), sbi);
    const uint32_t hb = hadd2(hmul2(pack_bf16((b[2 * i] - mb) * rb, (b[2 * i + 1] - mb) * rb), c2), sbi);
    a[2 * i] = bf_lo(ha); a[2 * i + 1] = bf_hi(ha); b[2 * i] = bf_lo(hb); b[2 * i + 1] = bf_hi(hb);
  }
  ln_stats2(a, b, ma, ra, mb, rb);
  ra *= 0.5f; rb *= 0.5f;
  TC(11);
  {
    const int s0 = 16 * c + 2 * w, kb = s0 >> 6, k0 = s0 & 63;
#pragma unroll
    for (int i = 0; i < 9; i++) {
      int atom = 2 * i + (l >> 4), ch = (l >> 2) & 3;
      uint8_t* base = g_h3 + ((size_t)(kb * 18 + atom) << 12) + (l & 3) * 4;
      int sw = (k0 >> 1) & 3;
      *reinterpret_cast<uint32_t*>(base + k0 * 64 + ((ch ^ sw) << 4)) = pack_bf16((a[2 * i] - ma) * ra, (a[2 * i + 1] - ma) * ra);
      *reinterpret_cast<uint32_t*>(base + (k0 + 1) * 64 + ((ch ^ sw) << 4)) = pack_bf16((b[2 * i] - mb) * rb, (b[2 * i + 1] - mb) * rb);
    }
  }
  TC(12);
  fence_async_glb();
  bar_sync(1, 256);
  TC(13);
  if (tid == 0) { TS(12); signal_cnt(&g_cnt[C_H3 + (c >> 2)]); TS(13); }
}

constexpr int JSK = 5;
struct Ring { uint32_t st, ph; };
template <bool G2, class T> __device__ __forceinline__ void ring_next(T& st, T& ph) {
  if (++st == NST) st = 0;
  ph ^= ((G2 ? 0xDu : 0x1u) >> st) & 1;
}
__device__ __forceinline__ void arrive_at(uint32_t bar, uint32_t cta) {
  asm volatile("{\n.reg .b32 r;\nmapa.shared::cluster.u32 r, %0, %1;\nmbarrier.arrive.shared::cluster.b64 _, [r];\n}" ::"r"(bar), "r"(cta) : "memory");
}
__device__ __forceinline__ uint32_t mapa(uint32_t a, uint32_t cta) { uint32_t r; asm("mapa.shared::cluster.u32 %0, %1, %2;" : "=r"(r) : "r"(a), "r"(cta)); return r; }
__device__ __forceinline__ void arrive_if(uint32_t a, uint32_t p) {
  asm volatile("{\n.reg .pred p;\nsetp.ne.u32 p, %1, 0;\n@p mbarrier.arrive.shared::cluster.b64 _, [%0];\n}" ::"r"(a), "r"(p) : "memory");
}
template <int NA> __device__ __forceinline__ void reg_fence_n(float (&d)[80]) {
#pragma unroll
  for (int i = 0; i < NA; i++) asm volatile("" : "+f"(d[i])::"memory");
}
template <int MODE>
__device__ __forceinline__ void gemm_main(float (&acc)[80], uint32_t da0, uint32_t da1, uint32_t db0, uint32_t db1, int wg, uint32_t rank,
                                          Ring& rg, uint32_t full0, uint32_t rdy) {
  static_assert(JSK == NST - 1, "the held slot is the first one that is not refilled by GEMM1");
  constexpr int NKB = MODE == 3 ? 36 : 32;
  constexpr uint32_t HA = 0x40000040u, HB = MODE == 3 ? 0x40000040u : 0x80000020u;
  constexpr uint32_t KA = 2048 >> 4, KB = MODE == 3 ? (32 >> 4) : (1024 >> 4);
  constexpr int NA = MODE ? 72 : 80;
  const uint32_t t = threadIdx.x & 127;
  const uint32_t eb = mapa(full0 + 8 * NST, rank);
  uint32_t pb = 0, rel = t == 0, prel = 0;
  int n = NKB - JSK;
#pragma unroll 1
  for (int pass = 0;; pass++) {
#pragma unroll 1
    do {
      const uint32_t so = rg.st * (STAGE >> 4);
      mbar_wait(full0 + 8 * rg.st, rg.ph);
      reg_fence_n<NA>(acc);
      wg_fence();
#pragma unroll
      for (int k = 0; k < 4; k++) {
        if (MODE == 0) wgmma_ss<160, 0, 1>(acc, da0 + so + k * KA, HA, db0 + so + k * KB, HB);
        else if (MODE == 3) wgmma_ss<144, 0, 0>(acc, da0 + so + k * KA, HA, db0 + so + k * KB, HB);
        else {
          wgmma_ss<96, 0, 1>(acc, da0 + so + k * KA, HA, db0 + so + k * KB, HB);
          wgmma_ss<48, 48, 1>(acc, da1 + so + k * KA, HA, db1 + so + k * KB, HB);
        }
      }
      wg_commit();
      wg_wait<1>();
      reg_fence_n<NA>(acc);
      arrive_if(pb, prel);
      pb = eb + 8 * rg.st; prel = rel;
      ring_next<MODE == 3>(rg.st, rg.ph);
    } while (--n);
    if (pass == 2 - wg) break;
    n = 1;
    if (pass == 0) {
      if (MODE != 3) prel = rel & wg;
      else { if (t == 1) pb = mapa(rdy, rank ^ 1); prel = t < 2; rel = 0; }
      n = JSK - 1 + wg;
      if (!wg) continue;
      wg_wait<0>();
      arrive_if(pb, prel);
      prel = 0;
    }
    bar_sync(1, 256);
  }
  wg_wait<0>();
  reg_fence_n<NA>(acc);
  if (MODE != 3) arrive_if(pb, prel & ~wg);
}

__device__ __forceinline__ float gelu_arg(float h) { return h * fmaf(8.0f * 0.044715f * 0.7978845608028654f, h * h, 2.0f * 0.7978845608028654f); }

__device__ __forceinline__ int kb2_order(int i) { const int wv = i / 6; return 6 * (i - 6 * wv) + ((0x431250 >> (4 * wv)) & 7); }

__device__ __forceinline__ void wait_flags(const unsigned* base, int n, int idx, unsigned target, uint64_t& ready) {
  if ((ready >> idx) & 1) return;
  const int l = threadIdx.x & 31;
  int it = 0;
  while (true) {
    unsigned a = l < n ? ld_acquire(base + l) : target, b = l + 32 < n ? ld_acquire(base + l + 32) : target;
    ready = (uint64_t)__ballot_sync(0xffffffffu, a >= target) | ((uint64_t)__ballot_sync(0xffffffffu, b >= target) << 32);
    if ((ready >> idx) & 1) break;
    if (FSLEEP) __nanosleep(FSLEEP);
    if (++it > (1 << 21)) __trap();
  }
  fence_async_glb();
}

__global__ void __launch_bounds__(NTHR, 1)
fused_kernel(const __grid_constant__ Maps maps, const Params p) {
  extern __shared__ uint8_t smem_raw[];
  __shared__ uint64_t bars[2 * NST + 6];
  __shared__ __align__(16) float red[128 + D_];
  __shared__ __align__(16) uint32_t smod[864];
  __shared__ __align__(128) uint8_t zblk[2048];

  uint8_t* smem = reinterpret_cast<uint8_t*>((reinterpret_cast<uintptr_t>(smem_raw) + 1023) & ~uintptr_t(1023));
  const uint32_t sbase = smem_u32(smem);
  const uint32_t full0 = smem_u32(bars), empty0 = smem_u32(bars + NST), gbar = smem_u32(bars + 2 * NST);
  const int tid = threadIdx.x, wg = tid >> 7, cta = blockIdx.x, t128 = tid & 127;
  const int q = cta >> 1, r = cta & 1;
  int gq, gi;
  {
    const int tq = q - 4;
    gq = q < 4 ? 0 : tq < 32 ? (tq & 7) : tq < 60 ? 1 + (tq - 32) % 7 : tq - 54;
    gi = q < 4 ? q : tq < 32 ? (tq >> 3) + (gq == 0 ? 4 : 0) : tq < 60 ? 4 + (tq - 32) / 7 : 8;
  }
  const int j1 = 2 * (8 * gq + (gq == 7) + gi) + r, grp = j1 / 11, m1 = j1 - 11 * grp;
  const bool helper = (m1 & 3) == 3;
  const int f1 = 384 * grp + (helper ? 192 : 128) * (m1 >> 2);
  const int d1 = 160 * (m1 & 3), flip = m1 >= 7;
  const int a1bytes = helper ? 24576 : 16384, b1bytes = helper ? 12288 : 20480;

  uint32_t xr[18];
  if (cta < 128 && wg < 2) {
    const uint32_t* xs = reinterpret_cast<const uint32_t*>(p.x) + (size_t)(16 * cta + 2 * (tid >> 5)) * 288 + (tid & 31);
#pragma unroll
    for (int i = 0; i < 9; i++) { xr[i] = __ldg(xs + 32 * i); xr[9 + i] = __ldg(xs + 288 + 32 * i); }
  }
  if (tid == 256) {
    mbar_init(gbar + 16, 1);
    asm volatile("fence.mbarrier_init.release.cluster;" ::: "memory");
    fence_async_smem();
    if (cta < 36) mod_issue(maps, cta, sbase, gbar + 16);
  }
  if (tid == 0) {
    TS(0);
#pragma unroll 1
    for (int i = 0; i < NST; i++) { mbar_init(full0 + 8 * i, 1); mbar_init(empty0 + 8 * i, 2); }
    mbar_init(gbar, 1); mbar_init(gbar + 8, 1); mbar_init(gbar + 24, 2); mbar_init(gbar + 32, 1); mbar_init(gbar + 40, 1);
    mbar_expect(gbar + 32, 18432);
    asm volatile("fence.mbarrier_init.release.cluster;" ::: "memory");
    fence_async_smem();
  }
  asm volatile("barrier.cluster.arrive.relaxed.aligned;\nbarrier.cluster.wait.aligned;" ::: "memory");
  auto load_a1 = [&](int st, int kb) {
    mbar_expect(full0 + 8 * st, a1bytes + b1bytes);
#pragma unroll 1
    for (int i = 0; i < a1bytes / 8192; i++) ((EF & 1) ? tma2d_h : tma2d)(sbase + st * STAGE + i * 8192, &maps.w1, f1 + 64 * i, 64 * kb, full0 + 8 * st);
  };
  if (wg == 2) {
    if (cta >= 36) {
      bar_sync(7, NTHR);
      if (t128 < 2) {
        const int off = (cta - 36) * 12352, len = min(12352, S_ * DF_ * 2 - off);
        prefetch_l2(reinterpret_cast<const uint8_t*>(t128 ? p.wr : p.wi) + off, len);
      }
    }
#pragma unroll 1
    for (int pass = 0; pass < SKIPN(2); pass++) {
      if (pass == 1 || cta >= 36) {
        if (pass == (cta >= 36 ? 0 : 1)) {
          bar_sync(6, NTHR);
          if (t128 == 0) {
            mbar_expect(gbar, 16384); bulk_ld(sbase + FS_G, T_G, 16384, gbar);
            if (cta >= 36 && cta < 108) mod_issue(maps, cta, sbase, gbar + 16);
          }
          if (cta < 128) phase_wt(p, cta, t128, smem);
          continue;
        }
      }
      if (cta < 108) {
        phase_mod(p, cta, t128, red, sbase, gbar + 16);
      }
    }
  } else {
    if (cta < SKIPN(128)) phase1(maps, cta, tid, smem, xr, smod);
    else {
      if (cta >= 36) asm volatile("bar.arrive 7, %0;" ::"n"(NTHR) : "memory");
      if (SKIPN(1)) asm volatile("bar.arrive 6, %0;" ::"n"(NTHR) : "memory");
    }
  }
  {
    const int task = cta + NCTA * wg;
    if (SKIPN(1) && task < DF_) phase2(maps, task, wg, t128, smem, gbar);
  }
  if (PFMODE != 0 && tid >= 256 && tid < 288 && cta < SKIPN(128)) {
    bar_sync(10, 288);
    if (tid == 256 && cta >= 32) {
#pragma unroll 1
      for (int g = PFMODE == 1 ? 0 : PFKB / 4; g < NG1; g++) prefetch_l2(reinterpret_cast<const uint8_t*>(p.w1) + (size_t)g * 2359296 + (cta - 32) * 24576, 24576);
    }
  }
  uint32_t x1r[18];
  if (wg < 2 && cta < SKIPN(128)) phase3(p, cta, tid, smem, gbar + 8, smod, x1r);
  __syncthreads();

  const bool g2 = q < 64;
  const int z2 = 8 * gq + gi;
  const int s2 = 128 * (z2 >> 2), d2 = 144 * (z2 & 3);
  const uint32_t rdy = gbar + 24, rcv = gbar + 32;
  constexpr int XST = (33 + 36 - JSK - 1) % NST;
  constexpr int ST0 = (32 - JSK - 1) % NST, ST1 = 31 % NST;

  if (wg == 2) {
    asm volatile("setmaxnreg.dec.sync.aligned.u32 40;");
    if (tid == 256) {
      int st = 0, ph = 1;
#pragma unroll 1
      for (int kb = 0; kb < 32; kb++) {
        mbar_wait(empty0 + 8 * st, ph);
        load_a1(st, kb);
        if (kb >= PF2K && kb < PF2K + PF2 && g2)
          prefetch_l2(reinterpret_cast<const uint8_t*>(p.w2) + (size_t)(36 * r + kb2_order(kb - PF2K)) * 262144 + q * 4096, 4096);
        if (++st == NST) { st = 0; ph ^= 1; }
      }
      if (g2) {
        st++;
#pragma unroll 1
        for (int i = 0; i < 36; i++) {
          const int kb = 36 * r + kb2_order(i);
          if (i == HOLDA) mbar_wait(gbar + 40, 0);
          mbar_wait(empty0 + 8 * st, ph);
          mbar_expect(full0 + 8 * st, 16384 + 18432);
          ((EF & 2) ? tma2d_h : tma2d)(sbase + st * STAGE, &maps.w2, s2, 64 * kb, full0 + 8 * st);
          ((EF & 2) ? tma2d_h : tma2d)(sbase + st * STAGE + 8192, &maps.w2, s2 + 64, 64 * kb, full0 + 8 * st);
          ring_next<true>(st, ph);
        }
        mbar_wait(empty0 + 8 * st, ph);
        mbar_expect(full0 + 8 * st, 18432);
#pragma unroll 1
        for (int i = 0; i < 3; i++) tma2d(sbase + st * STAGE + 18432 + i * 6144, &maps.x1, d2 + 48 * i, s2 + 64 * (r ^ 1), full0 + 8 * st);
      }
    } else if (tid >= 320) {
      const int t64 = tid - 320, sw = t64 >> 5;
      const uint32_t zs = smem_u32(zblk);
      for (int i = t64; i < 128; i += 64) reinterpret_cast<uint4*>(zblk)[i] = make_uint4(0, 0, 0, 0);
      fence_async_smem();
      bar_sync(8, 64);
      if (t64 == 32) {
        __nanosleep(ZSLEEP);
#pragma unroll 1
        for (int k = 0; k < 3; k++) {
          const int task = cta + NCTA * k;
          if (task < DF_) {
#pragma unroll 1
            for (int i = 0; i < 4; i++) {
              bulk_st(reinterpret_cast<uint8_t*>(g_WT) + (size_t)task * 8192 + i * 2048, zs, 2048);
              bulk_st(reinterpret_cast<uint8_t*>(g_Z1) + (size_t)(i < 2 ? task : DF_ + task) * 4096 + (i & 1) * 2048, zs, 2048);
              __nanosleep(ZS2);
            }
          }
        }
        if (cta < 128) {
#pragma unroll 1
          for (int i = 0; i < 10; i++) { bulk_st(reinterpret_cast<uint8_t*>(g_Z2) + (size_t)cta * 20480 + i * 2048, zs, 2048); __nanosleep(100); }
        }
        bulk_commit_wait();
      }
      __syncwarp();
      const uint32_t stg = sbase + (sw ? ST1 : ST0) * STAGE;
      const int kbA = (f1 >> 6) + (helper ? 2 : 1) * (sw ^ flip), kbB = helper ? (f1 >> 6) + 1 : kbA;
      const int dB = helper ? d1 + 32 * sw : d1 + 96;
      bar_sync(11 + sw, 160);
      if ((t64 & 31) == 0) { TS(sw ? 31 : 30); bulk_st(g_u + ((size_t)kbA * D_ + d1) * 128, stg, 96 * 128); }
      __syncwarp();
      bar_sync(13 + sw, 160);
      if ((t64 & 31) == 0) {
        bulk_st(g_u + ((size_t)kbB * D_ + dB) * 128, stg + 96 * 128, helper ? 32 * 128 : 64 * 128);
        if (helper) bulk_st(g_u + ((size_t)kbB * D_ + d1 + 64 + 16 * sw) * 128, stg + 128 * 128, 16 * 128);
        bulk_commit_wait();
        mbar_arrive(empty0 + 8 * (sw ? ST1 : ST0));
        if (sw == 0) TS(26);
        asm volatile("fence.acq_rel.gpu;" ::: "memory");
        asm volatile("red.relaxed.gpu.global.add.u32 [%0], 2;" ::"l"(&g_cnt[C_U + kbA]) : "memory");
        if (helper) signal_rlx(&g_cnt[C_U + kbB]);
        TS(sw ? 23 : 17);
      }
    } else if (tid >= 288) {
      const bool lead = tid == 288;
      uint64_t ready = 0;
      int st = 0, ph = 1;
#pragma unroll 1
      for (int kb = 0; kb < 32; kb++) {
        mbar_wait(empty0 + 8 * st, ph);
        wait_flags(g_cnt + C_H3, 32, kb, SKIPN(4), ready);
        if (lead) {
          const uint8_t* src = g_h3 + ((size_t)(kb * 18 + (d1 >> 5)) << 12);
          bulk_ld(sbase + st * STAGE + a1bytes, src, b1bytes, full0 + 8 * st);
        }
        if (++st == NST) { st = 0; ph ^= 1; }
      }
      if (g2) {
        ready = 0;
        st++;
#pragma unroll 1
        for (int i = 0; i < 36; i++) {
          const int kb = kb2_order(i);
          mbar_wait(empty0 + 8 * st, ph);
          wait_flags(g_cnt + C_U + 36 * r, 36, kb, 8, ready);
          if (lead) {
            bulk_ld(sbase + st * STAGE + 16384, g_u + ((size_t)(36 * r + kb) * D_ + d2) * 128, 18432, full0 + 8 * st);
            if (i == GOAT) mbar_arrive(gbar + 40);
          }
          ring_next<true>(st, ph);
        }
      }
    }
  } else {
    asm volatile("setmaxnreg.inc.sync.aligned.u32 232;");
    if (tid == 0) TS(14);
    const int wgu = __shfl_sync(0xffffffffu, wg, 0);
    const uint32_t sb4 = __shfl_sync(0xffffffffu, (sbase & 0x3FFFF) >> 4, 0), fullu = __shfl_sync(0xffffffffu, full0, 0);
    const int w = t128 >> 5, l = t128 & 31, g = l >> 2, t = l & 3;
    Ring rg = {0, 0};
    float acc[80];
    constexpr uint32_t LA = (8192 >> 4) << 16, LB = (4096 >> 4) << 16;
    {
      const int fa = f1 + (helper ? 128 : 64) * (wg ^ flip) + 16 * w + g, fb = helper ? f1 + 64 + 16 * w + g : fa;
      const float a0 = 0.5f * __bfloat162float(p.b1[fa]), a1 = 0.5f * __bfloat162float(p.b1[fa + 8]);
      const float b0 = 0.5f * __bfloat162float(p.b1[fb]), b1 = 0.5f * __bfloat162float(p.b1[fb + 8]);
#pragma unroll
      for (int i = 0; i < 80; i++) acc[i] = i < 48 ? ((i & 2) ? a1 : a0) : ((i & 2) ? b1 : b0);
      reg_fence(acc);
    }
    if (!helper) gemm_main<0>(acc, sb4 + (wgu ^ flip) * 512 + LA, 0, sb4 + 1024 + LB, 0, wgu, r, rg, fullu, rdy);
    else {
      float ac2[80];
#pragma unroll
      for (int i = 0; i < 72; i++) asm volatile("mov.b32 %0, %1;" : "=f"(ac2[i]) : "f"(acc[i]));
      gemm_main<1>(ac2, sb4 + (wgu ^ flip) * 1024 + LA, sb4 + 512 + LA, sb4 + 1536 + LB, sb4 + 1536 + (wgu ? 256 + LB + (2 << 16) : 2 * LB), wgu, r, rg, fullu, rdy);
#pragma unroll
      for (int i = 0; i < 72; i++) asm volatile("mov.b32 %0, %1;" : "=f"(acc[i]) : "f"(ac2[i]));
    }
    if (t128 == 0) { TS(wg ? 16 : 6); if (wg) TSC(24); }
    {
      const int mi = l >> 3, rr = l & 7;
      const uint32_t ad = sbase + (wg ? ST1 : ST0) * STAGE + (8 * (mi >> 1) + rr) * 128 + (((2 * w + (mi & 1)) ^ rr) << 4);
      float z[2][16];
      TE(0);
#pragma unroll
      for (int j = -1; j <= 5; j++) {
        if (j >= 1) {
          const float* a = &acc[16 * (j - 1)];
          const float* tt = z[(j - 1) & 1];
#pragma unroll
          for (int h = 0; h < 16; h += 8)
            stmatrix4t(ad + (2 * (j - 1) + (h >> 3)) * 2048, pack_bf16(fmaf(a[h], tt[h], a[h]), fmaf(a[h + 1], tt[h + 1], a[h + 1])),
                       pack_bf16(fmaf(a[h + 2], tt[h + 2], a[h + 2]), fmaf(a[h + 3], tt[h + 3], a[h + 3])),
                       pack_bf16(fmaf(a[h + 4], tt[h + 4], a[h + 4]), fmaf(a[h + 5], tt[h + 5], a[h + 5])),
                       pack_bf16(fmaf(a[h + 6], tt[h + 6], a[h + 6]), fmaf(a[h + 7], tt[h + 7], a[h + 7])));
        }
        if (j >= 0 && j < 5) {
#pragma unroll
          for (int e = 0; e < 16; e++) asm("tanh.approx.f32 %0, %0;" : "+f"(z[j & 1][e]));
        }
        if (j < 4) {
#pragma unroll
          for (int e = 0; e < 16; e++) z[(j + 1) & 1][e] = gelu_arg(acc[16 * (j + 1) + e]);
        }
        if (j == 3 || j == 5) { fence_async_smem(); asm volatile("bar.arrive %0, 160;" ::"r"((j == 3 ? 11 : 13) + wgu) : "memory"); }
        if (j < 5) {
          if (j >= 0) reg_fence(z[j & 1]);
          if (j < 4) reg_fence(z[(j + 1) & 1]);
          if (__builtin_expect(ad == 0x7ffffff0u + j, 0)) __trap();
          reg_fence(acc);
        }
        TE(j + 2);
      }
      if (t128 == 0) TS(wg ? 29 : 28);
    }
    if (g2) {
      const int mb = wgu ^ r;
      uint32_t gb[18];
      {
        float a0 = 0.f, a1 = 0.f;
        if (wg) { a0 = __bfloat162float(p.b2[s2 + 64 * mb + 16 * w + g]); a1 = __bfloat162float(p.b2[s2 + 64 * mb + 16 * w + 8 + g]); }
#pragma unroll
        for (int i = 0; i < 18; i++) gb[i] = ld_rlx(g_mod + 1440 + (d2 >> 1) + 4 * i + t);
#pragma unroll
        for (int i = 0; i < 72; i++) acc[i] = (i & 2) ? a1 : a0;
      }
      rg.st++;
      gemm_main<3>(acc, sb4 + mb * 512 + LA, 0, sb4 + 1024 + (1 << 16), 0, wgu, r, rg, fullu, rdy);
      if (t128 == 0) { TS(wg ? 20 : 19); if (wg) TSC(27); }
      const uint32_t sx = sbase + XST * STAGE;
      if (wgu == 0) {
        uint32_t rx, rb;
        asm("mapa.shared::cluster.u32 %0, %1, %2;" : "=r"(rx) : "r"(sx + t128 * 16), "r"(r ^ 1));
        asm("mapa.shared::cluster.u32 %0, %1, %2;" : "=r"(rb) : "r"(rcv), "r"(r ^ 1));
        mbar_wait_cluster(rdy, 0);
#pragma unroll
        for (int j = 0; j < 9; j++) {
          const float* a = &acc[8 * j];
          asm volatile("st.async.weak.shared::cluster.mbarrier::complete_tx::bytes.v4.b32 [%0], {%1,%2,%3,%4}, [%5];" ::"r"(rx + j * 2048),
                       "r"(pack_bf16(a[0], a[1])), "r"(pack_bf16(a[2], a[3])), "r"(pack_bf16(a[4], a[5])), "r"(pack_bf16(a[6], a[7])), "r"(rb) : "memory");
        }
        if (tid == 0) TS(21);
        if (w == 1) {
          unsigned old = 0;
          if (l == 0) old = atomicAdd(&g_cnt[C_DONE], 1u);
          old = __shfl_sync(0xffffffffu, old, 0);
          if (old == 127) {
            for (int i = l; i < C_TOTAL; i += 32) g_cnt[i] = 0;
            for (int i = l; i < 3 * D_; i += 32) g_mod[i] = 0;
          }
        } else if (w == 0) {
#pragma unroll 1
          for (int i = 0; i < 3; i++) {
            bar_sync(11 + i, 160);
            if (l == 0) tma_st2d(&maps.out, sx + 18432 + i * 6144, d2 + 48 * i, s2 + 64 * (r ^ 1));
            __syncwarp();
          }
          if (l == 0) { bulk_commit_wait_read(); TS(22); }
        }
      } else {
        mbar_wait(fullu + 8 * XST, rg.ph);
        mbar_wait_cluster(rcv, 0);
        if (t128 == 0) TS(5);
        const uint32_t xa = sx + 18432 + (16 * w + (l & 15)) * 96 + (l >> 4) * 16;
#pragma unroll
        for (int c = 0; c < 3; c++) {
          uint32_t pv[3][4], xv[3][4];
#pragma unroll
          for (int j = 0; j < 3; j++) {
            asm volatile("ld.shared.v4.b32 {%0,%1,%2,%3}, [%4];" : "=r"(pv[j][0]), "=r"(pv[j][1]), "=r"(pv[j][2]), "=r"(pv[j][3]) : "r"(sx + t128 * 16 + (3 * c + j) * 2048) : "memory");
            asm volatile("ldmatrix.sync.aligned.m8n8.x4.shared.b16 {%0,%1,%2,%3}, [%4];" : "=r"(xv[j][0]), "=r"(xv[j][1]), "=r"(xv[j][2]), "=r"(xv[j][3]) : "r"(xa + c * 6144 + j * 32) : "memory");
          }
#pragma unroll
          for (int j = 0; j < 3; j++) {
            const float* a = &acc[8 * (3 * c + j)];
            uint32_t o[4];
#pragma unroll
            for (int e = 0; e < 4; e++)
              o[e] = hadd2(xv[j][e], hmul2(gb[2 * (3 * c + j) + (e >> 1)], pack_bf16(a[2 * e] + bf_lo(pv[j][e]), a[2 * e + 1] + bf_hi(pv[j][e]))));
            stmatrix4(xa + c * 6144 + j * 32, o[0], o[1], o[2], o[3]);
          }
          fence_async_smem();
          asm volatile("bar.arrive %0, 160;" ::"r"(11 + c) : "memory");
        }
        if (t128 == 0) TS(7);
      }
    }
  }
}

typedef CUresult (*EncodeFn)(CUtensorMap*, CUtensorMapDataType, cuuint32_t, void*, const cuuint64_t*, const cuuint64_t*, const cuuint32_t*,
                             const cuuint32_t*, CUtensorMapInterleave, CUtensorMapSwizzle, CUtensorMapL2promotion, CUtensorMapFloatOOBfill);

void make_map(EncodeFn enc, CUtensorMap* m, CUtensorMapDataType dt, int rank, const void* ptr, const cuuint64_t* gd, const cuuint64_t* gs,
              const cuuint32_t* bx, CUtensorMapSwizzle swz, CUtensorMapL2promotion promo) {
  cuuint32_t es[3] = {1, 1, 1};
  enc(m, dt, rank, const_cast<void*>(ptr), gd, gs, bx, es, CU_TENSOR_MAP_INTERLEAVE_NONE, swz, promo, CU_TENSOR_MAP_FLOAT_OOB_FILL_NONE);
}
void make_map2(EncodeFn enc, CUtensorMap* m, const void* ptr, int rows, int cols, int bx0, int bx1, bool swz) {
  cuuint64_t gd[2] = {(cuuint64_t)cols, (cuuint64_t)rows}, gs[1] = {(cuuint64_t)cols * 2};
  cuuint32_t bx[2] = {(cuuint32_t)bx0, (cuuint32_t)bx1};
  make_map(enc, m, CU_TENSOR_MAP_DATA_TYPE_BFLOAT16, 2, ptr, gd, gs, bx, swz ? CU_TENSOR_MAP_SWIZZLE_128B : CU_TENSOR_MAP_SWIZZLE_NONE,
           CU_TENSOR_MAP_L2_PROMOTION_L2_256B);
}

}

extern "C" void kernel_launch(void* const* d_in, const int* in_sizes, int n_in, void* d_out, int out_size) {
  (void)in_sizes; (void)n_in; (void)out_size;
  static EncodeFn enc = nullptr;
  if (!enc) {
    void* f = nullptr; cudaDriverEntryPointQueryResult qr;
    cudaGetDriverEntryPoint("cuTensorMapEncodeTiled", &f, cudaEnableDefault, &qr);
    enc = reinterpret_cast<EncodeFn>(f);
    cudaFuncSetAttribute(fused_kernel, cudaFuncAttributeMaxDynamicSharedMemorySize, SMEM_BYTES);
  }
  Params p;
  p.x = (const __nv_bfloat16*)d_in[0]; p.wr = (const __nv_bfloat16*)d_in[1]; p.wi = (const __nv_bfloat16*)d_in[2];
  p.b1 = (const __nv_bfloat16*)d_in[5]; p.b2 = (const __nv_bfloat16*)d_in[7];
  p.c = (const __nv_bfloat16*)d_in[8]; p.wmod = (const __nv_bfloat16*)d_in[9];
  p.w1 = (const __nv_bfloat16*)d_in[4]; p.w2 = (const __nv_bfloat16*)d_in[6];
  p.out = (__nv_bfloat16*)d_out;
  static void *x1ptr = nullptr, *z1ptr = nullptr, *z2ptr = nullptr;
  if (!x1ptr) { cudaGetSymbolAddress(&x1ptr, g_x1); cudaGetSymbolAddress(&z1ptr, g_Z1); cudaGetSymbolAddress(&z2ptr, g_Z2); }
  Maps maps;
  make_map2(enc, &maps.w1, d_in[4], S_, F_, 64, 64, true);
  make_map2(enc, &maps.w2, d_in[6], F_, S_, 64, 64, true);
  make_map2(enc, &maps.x1, x1ptr, S_, D_, 48, 64, false);
  make_map2(enc, &maps.out, d_out, S_, D_, 48, 64, false);
  {
    cuuint64_t gd[2] = {1024, 2 * DF_}, gs[1] = {4096};
    cuuint32_t bx[2] = {8, 196};
    make_map(enc, &maps.z1, CU_TENSOR_MAP_DATA_TYPE_UINT32, 2, z1ptr, gd, gs, bx, CU_TENSOR_MAP_SWIZZLE_NONE, CU_TENSOR_MAP_L2_PROMOTION_NONE);
  }
  {
    cuuint64_t gd[2] = {6 * D_, D_}, gs[1] = {6 * D_ * 2};
    cuuint32_t bx[2] = {32, 192};
    make_map(enc, &maps.wm, CU_TENSOR_MAP_DATA_TYPE_BFLOAT16, 2, d_in[9], gd, gs, bx, CU_TENSOR_MAP_SWIZZLE_NONE, CU_TENSOR_MAP_L2_PROMOTION_NONE);
  }
  {
    cuuint64_t gd[3] = {8, 640, 128}, gs[2] = {32, 640 * 32};
    cuuint32_t bx[3] = {8, 1, 128};
    make_map(enc, &maps.z2, CU_TENSOR_MAP_DATA_TYPE_UINT32, 3, z2ptr, gd, gs, bx, CU_TENSOR_MAP_SWIZZLE_NONE, CU_TENSOR_MAP_L2_PROMOTION_NONE);
  }
  cudaLaunchConfig_t cfg = {};
  cfg.gridDim = dim3(NCTA); cfg.blockDim = dim3(NTHR); cfg.dynamicSmemBytes = SMEM_BYTES; cfg.stream = cudaStreamPerThread;
  cudaLaunchAttribute at[1];
  at[0].id = cudaLaunchAttributeClusterDimension; at[0].val.clusterDim.x = 2; at[0].val.clusterDim.y = 1; at[0].val.clusterDim.z = 1;
  cfg.attrs = at; cfg.numAttrs = 1;
  cudaLaunchKernelEx(&cfg, fused_kernel, maps, p);
}
```

```cpp
#include <cuda_runtime.h>
#include <cuda_bf16.h>
#include <cuda.h>
#include <stdint.h>

namespace {

constexpr int S_ = 2048, D_ = 576, DF_ = 289, F_ = 4608;
constexpr int NCTA = 132, NTHR = 384;
constexpr int STAGE = 36864, NST = 6;
constexpr int SMEM_BYTES = NST * STAGE + 1024;
constexpr int O_NRM = 0, O_B1 = 19456, O_Z1 = 38912, O_P2 = 59392, O_CF = 79872;
constexpr int O_RAW = 4 * STAGE;
constexpr int O_IN = 4 * STAGE, O_Y = O_IN + 19456, O_B3 = O_IN + 38912, O_MOD = O_IN + 57344;

__device__ __align__(128) const uint32_t T_TAB[5632] = {
0x3f803f80,0xbf803f80,0x3f803f80,0xbf803f80,0x3f803f80,0xbf803f80,0x3f803f80,0xbf803f80,0x3f803f80,0xbf803f80,0x3f803f80,0xbf803f80,
0x3f803f80,0xbf803f80,0x3f803f80,0xbf803f80,0x3f7f3f80,0xbdc90000,0x3f223f35,0xbf46bf35,0x3f753f7b,0xbe95be48,0x3ef13f0e,0xbf62bf55,
0x3f623f6d,0xbef1bec4,0x3e953ec4,0xbf75bf6d,0x3f463f55,0xbf22bf0e,0x3dc93e48,0xbf7fbf7b,0x3f7b3f80,0xbe480000,0xbe480000,0xbf7bbf80,
0x3f553f6d,0xbf0ebec4,0xbf0ebec4,0xbf55bf6d,0x3f0e3f35,0xbf55bf35,0xbf55bf35,0xbf0ebf35,0x3e483ec4,0xbf7bbf6d,0xbf7bbf6d,0xbe48bec4,
0x3f753f80,0xbe950000,0xbf62bf35,0xbef1bf35,0x3f223f55,0xbf46bf0e,0xbf7fbf7b,0x3dc9be48,0x3dc93ec4,0xbf7fbf6d,0xbf46bf6d,0x3f223ec4,
0xbef1be48,0xbf62bf7b,0xbe95bf0e,0x3f753f55,0x3f6d3f80,0xbec40000,0xbf6dbf80,0x3ec40000,0x3ec43f35,0xbf6dbf35,0xbec4bf35,0x3f6d3f35,
0xbec40000,0xbf6dbf80,0x3ec40000,0x3f6d3f80,0xbf6dbf35,0xbec4bf35,0x3f6d3f35,0x3ec43f35,0x3f623f80,0xbef10000,0xbe95bf35,0x3f753f35,
0x3dc93f0e,0xbf7fbf55,0x3f223e48,0x3f463f7b,0xbf46bec4,0xbf22bf6d,0x3f7f3f6d,0xbdc93ec4,0xbf75bf7b,0x3e95be48,0x3ef13f55,0xbf62bf0e,
0x3f553f80,0xbf0e0000,0x3f0e0000,0x3f553f80,0xbe483ec4,0xbf7bbf6d,0x3f7b3f6d,0xbe483ec4,0xbf7bbf35,0xbe48bf35,0x3e483f35,0xbf7bbf35,
0xbf0ebf6d,0x3f553ec4,0xbf55bec4,0xbf0ebf6d,0x3f463f80,0xbf220000,0x3f7f3f35,0x3dc93f35,0xbef13e48,0xbf62bf7b,0x3e953f55,0xbf75bf0e,
0xbf75bf6d,0x3e95bec4,0xbf62bec4,0xbef1bf6d,0x3dc9bf0e,0x3f7f3f55,0xbf22bf7b,0x3f463e48,0x3f353f80,0xbf350000,0x3f353f80,0xbf350000,
0xbf350000,0xbf35bf80,0xbf350000,0xbf35bf80,0xbf35bf80,0x3f350000,0xbf35bf80,0x3f350000,0x3f350000,0x3f353f80,0x3f350000,0x3f353f80,
0x3f223f80,0xbf460000,0xbdc93f35,0xbf7fbf35,0xbf62be48,0xbef1bf7b,0xbf75bf55,0x3e95bf0e,0xbe95bf6d,0x3f753ec4,0x3ef1bec4,0x3f623f6d,
0x3f7f3f0e,0x3dc93f55,0x3f463f7b,0xbf223e48,0x3f0e3f80,0xbf550000,0xbf550000,0xbf0ebf80,0xbf7bbec4,0xbe48bf6d,0xbe48bf6d,0x3f7b3ec4,
0x3e48bf35,0x3f7b3f35,0x3f7b3f35,0xbe483f35,0x3f553f6d,0xbf0e3ec4,0xbf0e3ec4,0xbf55bf6d,0x3ef13f80,0xbf620000,0xbf75bf35,0x3e95bf35,
0xbf7fbf0e,0x3dc9bf55,0x3f46be48,0x3f223f7b,0x3f22bec4,0x3f463f6d,0x3dc93f6d,0xbf7fbec4,0x3e953f7b,0xbf75be48,0xbf62bf55,0x3ef1bf0e,
0x3ec43f80,0xbf6d0000,0xbec4bf80,0x3f6d0000,0xbf6dbf35,0x3ec4bf35,0x3f6d3f35,0xbec43f35,0x3f6d0000,0x3ec43f80,0xbf6d0000,0xbec4bf80,
0xbec43f35,0xbf6dbf35,0x3ec4bf35,0x3f6d3f35,0x3e953f80,0xbf750000,0x3ef1bf35,0x3f623f35,0xbf46bf55,0x3f22bf0e,0x3dc93f7b,0xbf7fbe48,
0x3f7f3ec4,0xbdc93f6d,0xbf22bf6d,0x3f46bec4,0xbf623e48,0xbef1bf7b,0x3f753f0e,0xbe953f55,0x3e483f80,0xbf7b0000,0x3f7b0000,0x3e483f80,
0xbf0ebf6d,0x3f55bec4,0xbf553ec4,0xbf0ebf6d,0x3f553f35,0xbf0e3f35,0x3f0ebf35,0x3f553f35,0xbf7bbec4,0x3e48bf6d,0xbe483f6d,0xbf7bbec4,
0x3dc93f80,0xbf7f0000,0x3f463f35,0xbf223f35,0xbe95bf7b,0x3f75be48,0xbf62bf0e,0x3ef1bf55,0x3ef13f6d,0xbf623ec4,0x3f753ec4,0xbe953f6d,
0xbf22bf55,0x3f46bf0e,0xbf7fbe48,0x3dc9bf7b,0x3f80,0xbf800000,0x3f80,0xbf800000,0xbf80,0x3f800000,0xbf80,0x3f800000,
0x3f80,0xbf800000,0x3f80,0xbf800000,0xbf80,0x3f800000,0xbf80,0x3f800000,0xbdc93f80,0xbf7f0000,0xbf463f35,0xbf22bf35,
0x3e95bf7b,0x3f753e48,0x3f62bf0e,0x3ef13f55,0xbef13f6d,0xbf62bec4,0xbf753ec4,0xbe95bf6d,0x3f22bf55,0x3f463f0e,0x3f7fbe48,0x3dc93f7b,
0xbe483f80,0xbf7b0000,0xbf7b0000,0x3e48bf80,0x3f0ebf6d,0x3f553ec4,0x3f553ec4,0xbf0e3f6d,0xbf553f35,0xbf0ebf35,0xbf0ebf35,0x3f55bf35,
0x3f7bbec4,0x3e483f6d,0x3e483f6d,0xbf7b3ec4,0xbe953f80,0xbf750000,0xbef1bf35,0x3f62bf35,0x3f46bf55,0x3f223f0e,0xbdc93f7b,0xbf7f3e48,
0xbf7f3ec4,0xbdc9bf6d,0x3f22bf6d,0x3f463ec4,0x3f623e48,0xbef13f7b,0xbf753f0e,0xbe95bf55,0xbec43f80,0xbf6d0000,0x3ec4bf80,0x3f6d0000,
0x3f6dbf35,0x3ec43f35,0xbf6d3f35,0xbec4bf35,0xbf6d0000,0x3ec4bf80,0x3f6d0000,0xbec43f80,0x3ec43f35,0xbf6d3f35,0xbec4bf35,0x3f6dbf35,
0xbef13f80,0xbf620000,0x3f75bf35,0x3e953f35,0x3f7fbf0e,0x3dc93f55,0xbf46be48,0x3f22bf7b,0xbf22bec4,0x3f46bf6d,0xbdc93f6d,0xbf7f3ec4,
0xbe953f7b,0xbf753e48,0x3f62bf55,0x3ef13f0e,0xbf0e3f80,0xbf550000,0x3f550000,0xbf0e3f80,0x3f7bbec4,0xbe483f6d,0x3e48bf6d,0x3f7bbec4,
0xbe48bf35,0x3f7bbf35,0xbf7b3f35,0xbe48bf35,0xbf553f6d,0xbf0ebec4,0x3f0e3ec4,0xbf553f6d,0xbf223f80,0xbf460000,0x3dc93f35,0xbf7f3f35,
0x3f62be48,0xbef13f7b,0x3f75bf55,0x3e953f0e,0x3e95bf6d,0x3f75bec4,0xbef1bec4,0x3f62bf6d,0xbf7f3f0e,0x3dc9bf55,0xbf463f7b,0xbf22be48,
0xbf353f80,0xbf350000,0xbf353f80,0xbf350000,0x3f350000,0xbf353f80,0x3f350000,0xbf353f80,0x3f35bf80,0x3f350000,0x3f35bf80,0x3f350000,
0xbf350000,0x3f35bf80,0xbf350000,0x3f35bf80,0xbf463f80,0xbf220000,0xbf7f3f35,0x3dc9bf35,0x3ef13e48,0xbf623f7b,0xbe953f55,0xbf753f0e,
0x3f75bf6d,0x3e953ec4,0x3f62bec4,0xbef13f6d,0xbdc9bf0e,0x3f7fbf55,0x3f22bf7b,0x3f46be48,0xbf553f80,0xbf0e0000,0xbf0e0000,0x3f55bf80,
0x3e483ec4,0xbf7b3f6d,0xbf7b3f6d,0xbe48bec4,0x3f7bbf35,0xbe483f35,0xbe483f35,0xbf7b3f35,0x3f0ebf6d,0x3f55bec4,0x3f55bec4,0xbf0e3f6d,
0xbf623f80,0xbef10000,0x3e95bf35,0x3f75bf35,0xbdc93f0e,0xbf7f3f55,0xbf223e48,0x3f46bf7b,0x3f46bec4,0xbf223f6d,0xbf7f3f6d,0xbdc9bec4,
0x3f75bf7b,0x3e953e48,0xbef13f55,0xbf623f0e,0xbf6d3f80,0xbec40000,0x3f6dbf80,0x3ec40000,0xbec43f35,0xbf6d3f35,0x3ec4bf35,0x3f6dbf35,
0x3ec40000,0xbf6d3f80,0xbec40000,0x3f6dbf80,0x3f6dbf35,0xbec43f35,0xbf6d3f35,0x3ec4bf35,0xbf753f80,0xbe950000,0x3f62bf35,0xbef13f35,
0xbf223f55,0xbf463f0e,0x3f7fbf7b,0x3dc93e48,0xbdc93ec4,0xbf7f3f6d,0x3f46bf6d,0x3f22bec4,0x3ef1be48,0xbf623f7b,0x3e95bf0e,0x3f75bf55,
0xbf7b3f80,0xbe480000,0x3e480000,0xbf7b3f80,0xbf553f6d,0xbf0e3ec4,0x3f0ebec4,0xbf553f6d,0xbf0e3f35,0xbf553f35,0x3f55bf35,0xbf0e3f35,
0xbe483ec4,0xbf7b3f6d,0x3f7bbf6d,0xbe483ec4,0xbf7f3f80,0xbdc90000,0xbf223f35,0xbf463f35,0xbf753f7b,0xbe953e48,0xbef13f0e,0xbf623f55,
0xbf623f6d,0xbef13ec4,0xbe953ec4,0xbf753f6d,0xbf463f55,0xbf223f0e,0xbdc93e48,0xbf7f3f7b,0x3f803f80,0xbf803f80,0x3f803f80,0xbf803f80,
0x3f803f80,0xbf803f80,0x3f803f80,0xbf803f80,0x3f803f80,0xbf803f80,0x3f803f80,0xbf803f80,0x3f803f80,0xbf803f80,0x3f803f80,0xbf803f80,
0xbdc90000,0xbf7fbf80,0xbf46bf35,0xbf22bf35,0xbe95be48,0xbf75bf7b,0xbf62bf55,0xbef1bf0e,0xbef1bec4,0xbf62bf6d,0xbf75bf6d,0xbe95bec4,
0xbf22bf0e,0xbf46bf55,0xbf7fbf7b,0xbdc9be48,0xbf7bbf80,0x3e480000,0x3e480000,0x3f7b3f80,0xbf55bf6d,0x3f0e3ec4,0x3f0e3ec4,0x3f553f6d,
0xbf0ebf35,0x3f553f35,0x3f553f35,0x3f0e3f35,0xbe48bec4,0x3f7b3f6d,0x3f7b3f6d,0x3e483ec4,0x3e950000,0x3f753f80,0x3ef13f35,0xbf62bf35,
0x3f463f0e,0x3f223f55,0xbdc93e48,0xbf7fbf7b,0x3f7f3f6d,0x3dc93ec4,0xbf22bec4,0xbf46bf6d,0x3f623f7b,0xbef1be48,0xbf75bf55,0xbe95bf0e,
0x3f6d3f80,0xbec40000,0xbf6dbf80,0x3ec40000,0x3ec43f35,0xbf6dbf35,0xbec4bf35,0x3f6d3f35,0xbec40000,0xbf6dbf80,0x3ec40000,0x3f6d3f80,
0xbf6dbf35,0xbec4bf35,0x3f6d3f35,0x3ec43f35,0xbef10000,0xbf62bf80,0x3f753f35,0x3e953f35,0xbf7fbf55,0xbdc9bf0e,0x3f463f7b,0xbf22be48,
0xbf22bf6d,0x3f463ec4,0xbdc93ec4,0xbf7fbf6d,0x3e95be48,0x3f753f7b,0xbf62bf0e,0xbef1bf55,0xbf55bf80,0x3f0e0000,0xbf0e0000,0xbf55bf80,
0x3e48bec4,0x3f7b3f6d,0xbf7bbf6d,0x3e48bec4,0x3f7b3f35,0x3e483f35,0xbe48bf35,0x3f7b3f35,0x3f0e3f6d,0xbf55bec4,0x3f553ec4,0x3f0e3f6d,
0x3f220000,0x3f463f80,0xbdc9bf35,0x3f7f3f35,0x3f623f7b,0xbef13e48,0x3f753f0e,0x3e953f55,0xbe953ec4,0xbf75bf6d,0x3ef13f6d,0xbf62bec4,
0xbf7fbf55,0x3dc9bf0e,0xbf46be48,0xbf22bf7b,0x3f353f80,0xbf350000,0x3f353f80,0xbf350000,0xbf350000,0xbf35bf80,0xbf350000,0xbf35bf80,
0xbf35bf80,0x3f350000,0xbf35bf80,0x3f350000,0x3f350000,0x3f353f80,0x3f350000,0x3f353f80,0xbf460000,0xbf22bf80,0xbf7fbf35,0x3dc9bf35,
0xbef1bf7b,0x3f623e48,0x3e95bf0e,0x3f753f55,0x3f753ec4,0x3e953f6d,0x3f623f6d,0xbef13ec4,0x3dc93f55,0xbf7fbf0e,0xbf223e48,0xbf46bf7b,
0xbf0ebf80,0x3f550000,0x3f550000,0x3f0e3f80,0x3f7b3ec4,0x3e483f6d,0x3e483f6d,0xbf7bbec4,0xbe483f35,0xbf7bbf35,0xbf7bbf35,0x3e48bf35,
0xbf55bf6d,0x3f0ebec4,0x3f0ebec4,0x3f553f6d,0x3f620000,0x3ef13f80,0xbe953f35,0xbf75bf35,0xbdc93f55,0xbf7fbf0e,0xbf22bf7b,0x3f46be48,
0xbf46bf6d,0x3f22bec4,0x3f7f3ec4,0x3dc93f6d,0x3f753e48,0x3e953f7b,0xbef13f0e,0xbf62bf55,0x3ec43f80,0xbf6d0000,0xbec4bf80,0x3f6d0000,
0xbf6dbf35,0x3ec4bf35,0x3f6d3f35,0xbec43f35,0x3f6d0000,0x3ec43f80,0xbf6d0000,0xbec4bf80,0xbec43f35,0xbf6dbf35,0x3ec4bf35,0x3f6d3f35,
0xbf750000,0xbe95bf80,0x3f623f35,0xbef13f35,0x3f22bf0e,0x3f463f55,0xbf7fbe48,0xbdc9bf7b,0xbdc93f6d,0xbf7fbec4,0x3f46bec4,0x3f223f6d,
0xbef1bf7b,0x3f62be48,0xbe953f55,0xbf75bf0e,0xbe48bf80,0x3f7b0000,0xbf7b0000,0xbe48bf80,0x3f0e3f6d,0xbf553ec4,0x3f55bec4,0x3f0e3f6d,
0xbf55bf35,0x3f0ebf35,0xbf0e3f35,0xbf55bf35,0x3f7b3ec4,0xbe483f6d,0x3e48bf6d,0x3f7b3ec4,0x3f7f0000,0x3dc93f80,0x3f22bf35,0x3f463f35,
0xbf753e48,0xbe95bf7b,0xbef13f55,0xbf62bf0e,0x3f62bec4,0x3ef13f6d,0x3e95bf6d,0x3f753ec4,0xbf463f0e,0xbf22bf55,0xbdc93f7b,0xbf7fbe48,
0x3f80,0xbf800000,0x3f80,0xbf800000,0xbf80,0x3f800000,0xbf80,0x3f800000,0x3f80,0xbf800000,0x3f80,0xbf800000,
0xbf80,0x3f800000,0xbf80,0x3f800000,0xbf7f0000,0x3dc9bf80,0xbf22bf35,0x3f46bf35,0x3f753e48,0xbe953f7b,0x3ef13f55,0xbf623f0e,
0xbf62bec4,0x3ef1bf6d,0xbe95bf6d,0x3f75bec4,0x3f463f0e,0xbf223f55,0x3dc93f7b,0xbf7f3e48,0x3e48bf80,0x3f7b0000,0x3f7b0000,0xbe483f80,
0xbf0e3f6d,0xbf55bec4,0xbf55bec4,0x3f0ebf6d,0x3f55bf35,0x3f0e3f35,0x3f0e3f35,0xbf553f35,0xbf7b3ec4,0xbe48bf6d,0xbe48bf6d,0x3f7bbec4,
0x3f750000,0xbe953f80,0xbf623f35,0xbef1bf35,0xbf22bf0e,0x3f46bf55,0x3f7fbe48,0xbdc93f7b,0x3dc93f6d,0xbf7f3ec4,0xbf46bec4,0x3f22bf6d,
0x3ef1bf7b,0x3f623e48,0x3e953f55,0xbf753f0e,0xbec43f80,0xbf6d0000,0x3ec4bf80,0x3f6d0000,0x3f6dbf35,0x3ec43f35,0xbf6d3f35,0xbec4bf35,
0xbf6d0000,0x3ec4bf80,0x3f6d0000,0xbec43f80,0x3ec43f35,0xbf6d3f35,0xbec4bf35,0x3f6dbf35,0xbf620000,0x3ef1bf80,0x3e953f35,0xbf753f35,
0x3dc93f55,0xbf7f3f0e,0x3f22bf7b,0x3f463e48,0x3f46bf6d,0x3f223ec4,0xbf7f3ec4,0x3dc9bf6d,0xbf753e48,0x3e95bf7b,0x3ef13f0e,0xbf623f55,
0x3f0ebf80,0x3f550000,0xbf550000,0x3f0ebf80,0xbf7b3ec4,0x3e48bf6d,0xbe483f6d,0xbf7b3ec4,0x3e483f35,0xbf7b3f35,0x3f7bbf35,0x3e483f35,
0x3f55bf6d,0x3f0e3ec4,0xbf0ebec4,0x3f55bf6d,0x3f460000,0xbf223f80,0x3f7fbf35,0x3dc93f35,0x3ef1bf7b,0x3f62be48,0xbe95bf0e,0x3f75bf55,
0xbf753ec4,0x3e95bf6d,0xbf623f6d,0xbef1bec4,0xbdc93f55,0xbf7f3f0e,0x3f223e48,0xbf463f7b,0xbf353f80,0xbf350000,0xbf353f80,0xbf350000,
0x3f350000,0xbf353f80,0x3f350000,0xbf353f80,0x3f35bf80,0x3f350000,0x3f35bf80,0x3f350000,0xbf350000,0x3f35bf80,0xbf350000,0x3f35bf80,
0xbf220000,0x3f46bf80,0x3dc9bf35,0x3f7fbf35,0xbf623f7b,0xbef1be48,0xbf753f0e,0x3e95bf55,0x3e953ec4,0xbf753f6d,0xbef13f6d,0xbf623ec4,
0x3f7fbf55,0x3dc93f0e,0x3f46be48,0xbf223f7b,0x3f55bf80,0x3f0e0000,0x3f0e0000,0xbf553f80,0xbe48bec4,0x3f7bbf6d,0x3f7bbf6d,0x3e483ec4,
0xbf7b3f35,0x3e48bf35,0x3e48bf35,0x3f7bbf35,0xbf0e3f6d,0xbf553ec4,0xbf553ec4,0x3f0ebf6d,0x3ef10000,0xbf623f80,0xbf753f35,0x3e95bf35,
0x3f7fbf55,0xbdc93f0e,0xbf463f7b,0xbf223e48,0x3f22bf6d,0x3f46bec4,0x3dc93ec4,0xbf7f3f6d,0xbe95be48,0x3f75bf7b,0x3f62bf0e,0xbef13f55,
0xbf6d3f80,0xbec40000,0x3f6dbf80,0x3ec40000,0xbec43f35,0xbf6d3f35,0x3ec4bf35,0x3f6dbf35,0x3ec40000,0xbf6d3f80,0xbec40000,0x3f6dbf80,
0x3f6dbf35,0xbec43f35,0xbf6d3f35,0x3ec4bf35,0xbe950000,0x3f75bf80,0xbef13f35,0xbf623f35,0xbf463f0e,0x3f22bf55,0x3dc93e48,0xbf7f3f7b,
0xbf7f3f6d,0x3dc9bec4,0x3f22bec4,0xbf463f6d,0xbf623f7b,0xbef13e48,0x3f75bf55,0xbe953f0e,0x3f7bbf80,0x3e480000,0xbe480000,0x3f7bbf80,
0x3f55bf6d,0x3f0ebec4,0xbf0e3ec4,0x3f55bf6d,0x3f0ebf35,0x3f55bf35,0xbf553f35,0x3f0ebf35,0x3e48bec4,0x3f7bbf6d,0xbf7b3f6d,0x3e48bec4,
0x3dc90000,0xbf7f3f80,0x3f46bf35,0xbf223f35,0x3e95be48,0xbf753f7b,0x3f62bf55,0xbef13f0e,0x3ef1bec4,0xbf623f6d,0x3f75bf6d,0xbe953ec4,
0x3f22bf0e,0xbf463f55,0x3f7fbf7b,0xbdc93e48,0x3f803f80,0xbf803f80,0x3f803f80,0xbf803f80,0x3f803f80,0xbf803f80,0x3f803f80,0xbf803f80,
0x3f803f80,0xbf803f80,0x3f803f80,0xbf803f80,0x3f803f80,0xbf803f80,0x3f803f80,0xbf803f80,0xbf7fbf80,0x3dc90000,0xbf22bf35,0x3f463f35,
0xbf75bf7b,0x3e953e48,0xbef1bf0e,0x3f623f55,0xbf62bf6d,0x3ef13ec4,0xbe95bec4,0x3f753f6d,0xbf46bf55,0x3f223f0e,0xbdc9be48,0x3f7f3f7b,
0x3f7b3f80,0xbe480000,0xbe480000,0xbf7bbf80,0x3f553f6d,0xbf0ebec4,0xbf0ebec4,0xbf55bf6d,0x3f0e3f35,0xbf55bf35,0xbf55bf35,0xbf0ebf35,
0x3e483ec4,0xbf7bbf6d,0xbf7bbf6d,0xbe48bec4,0xbf75bf80,0x3e950000,0x3f623f35,0x3ef13f35,0xbf22bf55,0x3f463f0e,0x3f7f3f7b,0xbdc93e48,
0xbdc9bec4,0x3f7f3f6d,0x3f463f6d,0xbf22bec4,0x3ef13e48,0x3f623f7b,0x3e953f0e,0xbf75bf55,0x3f6d3f80,0xbec40000,0xbf6dbf80,0x3ec40000,
0x3ec43f35,0xbf6dbf35,0xbec4bf35,0x3f6d3f35,0xbec40000,0xbf6dbf80,0x3ec40000,0x3f6d3f80,0xbf6dbf35,0xbec4bf35,0x3f6d3f35,0x3ec43f35,
0xbf62bf80,0x3ef10000,0x3e953f35,0xbf75bf35,0xbdc9bf0e,0x3f7f3f55,0xbf22be48,0xbf46bf7b,0x3f463ec4,0x3f223f6d,0xbf7fbf6d,0x3dc9bec4,
0x3f753f7b,0xbe953e48,0xbef1bf55,0x3f623f0e,0x3f553f80,0xbf0e0000,0x3f0e0000,0x3f553f80,0xbe483ec4,0xbf7bbf6d,0x3f7b3f6d,0xbe483ec4,
0xbf7bbf35,0xbe48bf35,0x3e483f35,0xbf7bbf35,0xbf0ebf6d,0x3f553ec4,0xbf55bec4,0xbf0ebf6d,0xbf46bf80,0x3f220000,0xbf7fbf35,0xbdc9bf35,
0x3ef1be48,0x3f623f7b,0xbe95bf55,0x3f753f0e,0x3f753f6d,0xbe953ec4,0x3f623ec4,0x3ef13f6d,0xbdc93f0e,0xbf7fbf55,0x3f223f7b,0xbf46be48,
0x3f353f80,0xbf350000,0x3f353f80,0xbf350000,0xbf350000,0xbf35bf80,0xbf350000,0xbf35bf80,0xbf35bf80,0x3f350000,0xbf35bf80,0x3f350000,
0x3f350000,0x3f353f80,0x3f350000,0x3f353f80,0xbf22bf80,0x3f460000,0x3dc9bf35,0x3f7f3f35,0x3f623e48,0x3ef13f7b,0x3f753f55,0xbe953f0e,
0x3e953f6d,0xbf75bec4,0xbef13ec4,0xbf62bf6d,0xbf7fbf0e,0xbdc9bf55,0xbf46bf7b,0x3f22be48,0x3f0e3f80,0xbf550000,0xbf550000,0xbf0ebf80,
0xbf7bbec4,0xbe48bf6d,0xbe48bf6d,0x3f7b3ec4,0x3e48bf35,0x3f7b3f35,0x3f7b3f35,0xbe483f35,0x3f553f6d,0xbf0e3ec4,0xbf0e3ec4,0xbf55bf6d,
0xbef1bf80,0x3f620000,0x3f753f35,0xbe953f35,0x3f7f3f0e,0xbdc93f55,0xbf463e48,0xbf22bf7b,0xbf223ec4,0xbf46bf6d,0xbdc9bf6d,0x3f7f3ec4,
0xbe95bf7b,0x3f753e48,0x3f623f55,0xbef13f0e,0x3ec43f80,0xbf6d0000,0xbec4bf80,0x3f6d0000,0xbf6dbf35,0x3ec4bf35,0x3f6d3f35,0xbec43f35,
0x3f6d0000,0x3ec43f80,0xbf6d0000,0xbec4bf80,0xbec43f35,0xbf6dbf35,0x3ec4bf35,0x3f6d3f35,0xbe95bf80,0x3f750000,0xbef13f35,0xbf62bf35,
0x3f463f55,0xbf223f0e,0xbdc9bf7b,0x3f7f3e48,0xbf7fbec4,0x3dc9bf6d,0x3f223f6d,0xbf463ec4,0x3f62be48,0x3ef13f7b,0xbf75bf0e,0x3e95bf55,
0x3e483f80,0xbf7b0000,0x3f7b0000,0x3e483f80,0xbf0ebf6d,0x3f55bec4,0xbf553ec4,0xbf0ebf6d,0x3f553f35,0xbf0e3f35,0x3f0ebf35,0x3f553f35,
0xbf7bbec4,0x3e48bf6d,0xbe483f6d,0xbf7bbec4,0xbdc9bf80,0x3f7f0000,0xbf46bf35,0x3f22bf35,0x3e953f7b,0xbf753e48,0x3f623f0e,0xbef13f55,
0xbef1bf6d,0x3f62bec4,0xbf75bec4,0x3e95bf6d,0x3f223f55,0xbf463f0e,0x3f7f3e48,0xbdc93f7b,0x3f80,0xbf800000,0x3f80,0xbf800000,
0xbf80,0x3f800000,0xbf80,0x3f800000,0x3f80,0xbf800000,0x3f80,0xbf800000,0xbf80,0x3f800000,0xbf80,0x3f800000,
0x3dc9bf80,0x3f7f0000,0x3f46bf35,0x3f223f35,0xbe953f7b,0xbf75be48,0xbf623f0e,0xbef1bf55,0x3ef1bf6d,0x3f623ec4,0x3f75bec4,0x3e953f6d,
0xbf223f55,0xbf46bf0e,0xbf7f3e48,0xbdc9bf7b,0xbe483f80,0xbf7b0000,0xbf7b0000,0x3e48bf80,0x3f0ebf6d,0x3f553ec4,0x3f553ec4,0xbf0e3f6d,
0xbf553f35,0xbf0ebf35,0xbf0ebf35,0x3f55bf35,0x3f7bbec4,0x3e483f6d,0x3e483f6d,0xbf7b3ec4,0x3e95bf80,0x3f750000,0x3ef13f35,0xbf623f35,
0xbf463f55,0xbf22bf0e,0x3dc9bf7b,0x3f7fbe48,0x3f7fbec4,0x3dc93f6d,0xbf223f6d,0xbf46bec4,0xbf62be48,0x3ef1bf7b,0x3f75bf0e,0x3e953f55,
0xbec43f80,0xbf6d0000,0x3ec4bf80,0x3f6d0000,0x3f6dbf35,0x3ec43f35,0xbf6d3f35,0xbec4bf35,0xbf6d0000,0x3ec4bf80,0x3f6d0000,0xbec43f80,
0x3ec43f35,0xbf6d3f35,0xbec4bf35,0x3f6dbf35,0x3ef1bf80,0x3f620000,0xbf753f35,0xbe95bf35,0xbf7f3f0e,0xbdc9bf55,0x3f463e48,0xbf223f7b,
0x3f223ec4,0xbf463f6d,0x3dc9bf6d,0x3f7fbec4,0x3e95bf7b,0x3f75be48,0xbf623f55,0xbef1bf0e,0xbf0e3f80,0xbf550000,0x3f550000,0xbf0e3f80,
0x3f7bbec4,0xbe483f6d,0x3e48bf6d,0x3f7bbec4,0xbe48bf35,0x3f7bbf35,0xbf7b3f35,0xbe48bf35,0xbf553f6d,0xbf0ebec4,0x3f0e3ec4,0xbf553f6d,
0x3f22bf80,0x3f460000,0xbdc9bf35,0x3f7fbf35,0xbf623e48,0x3ef1bf7b,0xbf753f55,0xbe95bf0e,0xbe953f6d,0xbf753ec4,0x3ef13ec4,0xbf623f6d,
0x3f7fbf0e,0xbdc93f55,0x3f46bf7b,0x3f223e48,0xbf353f80,0xbf350000,0xbf353f80,0xbf350000,0x3f350000,0xbf353f80,0x3f350000,0xbf353f80,
0x3f35bf80,0x3f350000,0x3f35bf80,0x3f350000,0xbf350000,0x3f35bf80,0xbf350000,0x3f35bf80,0x3f46bf80,0x3f220000,0x3f7fbf35,0xbdc93f35,
0xbef1be48,0x3f62bf7b,0x3e95bf55,0x3f75bf0e,0xbf753f6d,0xbe95bec4,0xbf623ec4,0x3ef1bf6d,0x3dc93f0e,0xbf7f3f55,0xbf223f7b,0xbf463e48,
0xbf553f80,0xbf0e0000,0xbf0e0000,0x3f55bf80,0x3e483ec4,0xbf7b3f6d,0xbf7b3f6d,0xbe48bec4,0x3f7bbf35,0xbe483f35,0xbe483f35,0xbf7b3f35,
0x3f0ebf6d,0x3f55bec4,0x3f55bec4,0xbf0e3f6d,0x3f62bf80,0x3ef10000,0xbe953f35,0xbf753f35,0x3dc9bf0e,0x3f7fbf55,0x3f22be48,0xbf463f7b,
0xbf463ec4,0x3f22bf6d,0x3f7fbf6d,0x3dc93ec4,0xbf753f7b,0xbe95be48,0x3ef1bf55,0x3f62bf0e,0xbf6d3f80,0xbec40000,0x3f6dbf80,0x3ec40000,
0xbec43f35,0xbf6d3f35,0x3ec4bf35,0x3f6dbf35,0x3ec40000,0xbf6d3f80,0xbec40000,0x3f6dbf80,0x3f6dbf35,0xbec43f35,0xbf6d3f35,0x3ec4bf35,
0x3f75bf80,0x3e950000,0xbf623f35,0x3ef1bf35,0x3f22bf55,0x3f46bf0e,0xbf7f3f7b,0xbdc9be48,0x3dc9bec4,0x3f7fbf6d,0xbf463f6d,0xbf223ec4,
0xbef13e48,0x3f62bf7b,0xbe953f0e,0xbf753f55,0xbf7b3f80,0xbe480000,0x3e480000,0xbf7b3f80,0xbf553f6d,0xbf0e3ec4,0x3f0ebec4,0xbf553f6d,
0xbf0e3f35,0xbf553f35,0x3f55bf35,0xbf0e3f35,0xbe483ec4,0xbf7b3f6d,0x3f7bbf6d,0xbe483ec4,0x3f7fbf80,0x3dc90000,0x3f22bf35,0x3f46bf35,
0x3f75bf7b,0x3e95be48,0x3ef1bf0e,0x3f62bf55,0x3f62bf6d,0x3ef1bec4,0x3e95bec4,0x3f75bf6d,0x3f46bf55,0x3f22bf0e,0x3dc9be48,0x3f7fbf7b,
0x3f803f80,0xbf803f80,0x3f803f80,0xbf803f80,0x3f803f80,0xbf803f80,0x3f803f80,0xbf803f80,0x3f803f80,0xbf803f80,0x3f803f80,0xbf803f80,
0x3f803f80,0xbf803f80,0x3f803f80,0xbf803f80,0x3dc90000,0x3f7f3f80,0x3f463f35,0x3f223f35,0x3e953e48,0x3f753f7b,0x3f623f55,0x3ef13f0e,
0x3ef13ec4,0x3f623f6d,0x3f753f6d,0x3e953ec4,0x3f223f0e,0x3f463f55,0x3f7f3f7b,0x3dc93e48,0xbf7bbf80,0x3e480000,0x3e480000,0x3f7b3f80,
0xbf55bf6d,0x3f0e3ec4,0x3f0e3ec4,0x3f553f6d,0xbf0ebf35,0x3f553f35,0x3f553f35,0x3f0e3f35,0xbe48bec4,0x3f7b3f6d,0x3f7b3f6d,0x3e483ec4,
0xbe950000,0xbf75bf80,0xbef1bf35,0x3f623f35,0xbf46bf0e,0xbf22bf55,0x3dc9be48,0x3f7f3f7b,0xbf7fbf6d,0xbdc9bec4,0x3f223ec4,0x3f463f6d,
0xbf62bf7b,0x3ef13e48,0x3f753f55,0x3e953f0e,0x3f6d3f80,0xbec40000,0xbf6dbf80,0x3ec40000,0x3ec43f35,0xbf6dbf35,0xbec4bf35,0x3f6d3f35,
0xbec40000,0xbf6dbf80,0x3ec40000,0x3f6d3f80,0xbf6dbf35,0xbec4bf35,0x3f6d3f35,0x3ec43f35,0x3ef10000,0x3f623f80,0xbf75bf35,0xbe95bf35,
0x3f7f3f55,0x3dc93f0e,0xbf46bf7b,0x3f223e48,0x3f223f6d,0xbf46bec4,0x3dc9bec4,0x3f7f3f6d,0xbe953e48,0xbf75bf7b,0x3f623f0e,0x3ef13f55,
0xbf55bf80,0x3f0e0000,0xbf0e0000,0xbf55bf80,0x3e48bec4,0x3f7b3f6d,0xbf7bbf6d,0x3e48bec4,0x3f7b3f35,0x3e483f35,0xbe48bf35,0x3f7b3f35,
0x3f0e3f6d,0xbf55bec4,0x3f553ec4,0x3f0e3f6d,0xbf220000,0xbf46bf80,0x3dc93f35,0xbf7fbf35,0xbf62bf7b,0x3ef1be48,0xbf75bf0e,0xbe95bf55,
0x3e95bec4,0x3f753f6d,0xbef1bf6d,0x3f623ec4,0x3f7f3f55,0xbdc93f0e,0x3f463e48,0x3f223f7b,0x3f353f80,0xbf350000,0x3f353f80,0xbf350000,
0xbf350000,0xbf35bf80,0xbf350000,0xbf35bf80,0xbf35bf80,0x3f350000,0xbf35bf80,0x3f350000,0x3f350000,0x3f353f80,0x3f350000,0x3f353f80,
0x3f460000,0x3f223f80,0x3f7f3f35,0xbdc93f35,0x3ef13f7b,0xbf62be48,0xbe953f0e,0xbf75bf55,0xbf75bec4,0xbe95bf6d,0xbf62bf6d,0x3ef1bec4,
0xbdc9bf55,0x3f7f3f0e,0x3f22be48,0x3f463f7b,0xbf0ebf80,0x3f550000,0x3f550000,0x3f0e3f80,0x3f7b3ec4,0x3e483f6d,0x3e483f6d,0xbf7bbec4,
0xbe483f35,0xbf7bbf35,0xbf7bbf35,0x3e48bf35,0xbf55bf6d,0x3f0ebec4,0x3f0ebec4,0x3f553f6d,0xbf620000,0xbef1bf80,0x3e95bf35,0x3f753f35,
0x3dc9bf55,0x3f7f3f0e,0x3f223f7b,0xbf463e48,0x3f463f6d,0xbf223ec4,0xbf7fbec4,0xbdc9bf6d,0xbf75be48,0xbe95bf7b,0x3ef1bf0e,0x3f623f55,
0x3ec43f80,0xbf6d0000,0xbec4bf80,0x3f6d0000,0xbf6dbf35,0x3ec4bf35,0x3f6d3f35,0xbec43f35,0x3f6d0000,0x3ec43f80,0xbf6d0000,0xbec4bf80,
0xbec43f35,0xbf6dbf35,0x3ec4bf35,0x3f6d3f35,0x3f750000,0x3e953f80,0xbf62bf35,0x3ef1bf35,0xbf223f0e,0xbf46bf55,0x3f7f3e48,0x3dc93f7b,
0x3dc9bf6d,0x3f7f3ec4,0xbf463ec4,0xbf22bf6d,0x3ef13f7b,0xbf623e48,0x3e95bf55,0x3f753f0e,0xbe48bf80,0x3f7b0000,0xbf7b0000,0xbe48bf80,
0x3f0e3f6d,0xbf553ec4,0x3f55bec4,0x3f0e3f6d,0xbf55bf35,0x3f0ebf35,0xbf0e3f35,0xbf55bf35,0x3f7b3ec4,0xbe483f6d,0x3e48bf6d,0x3f7b3ec4,
0xbf7f0000,0xbdc9bf80,0xbf223f35,0xbf46bf35,0x3f75be48,0x3e953f7b,0x3ef1bf55,0x3f623f0e,0xbf623ec4,0xbef1bf6d,0xbe953f6d,0xbf75bec4,
0x3f46bf0e,0x3f223f55,0x3dc9bf7b,0x3f7f3e48,0x3f80,0xbf800000,0x3f80,0xbf800000,0xbf80,0x3f800000,0xbf80,0x3f800000,
0x3f80,0xbf800000,0x3f80,0xbf800000,0xbf80,0x3f800000,0xbf80,0x3f800000,0x3f7f0000,0xbdc93f80,0x3f223f35,0xbf463f35,
0xbf75be48,0x3e95bf7b,0xbef1bf55,0x3f62bf0e,0x3f623ec4,0xbef13f6d,0x3e953f6d,0xbf753ec4,0xbf46bf0e,0x3f22bf55,0xbdc9bf7b,0x3f7fbe48,
0x3e48bf80,0x3f7b0000,0x3f7b0000,0xbe483f80,0xbf0e3f6d,0xbf55bec4,0xbf55bec4,0x3f0ebf6d,0x3f55bf35,0x3f0e3f35,0x3f0e3f35,0xbf553f35,
0xbf7b3ec4,0xbe48bf6d,0xbe48bf6d,0x3f7bbec4,0xbf750000,0x3e95bf80,0x3f62bf35,0x3ef13f35,0x3f223f0e,0xbf463f55,0xbf7f3e48,0x3dc9bf7b,
0xbdc9bf6d,0x3f7fbec4,0x3f463ec4,0xbf223f6d,0xbef13f7b,0xbf62be48,0xbe95bf55,0x3f75bf0e,0xbec43f80,0xbf6d0000,0x3ec4bf80,0x3f6d0000,
0x3f6dbf35,0x3ec43f35,0xbf6d3f35,0xbec4bf35,0xbf6d0000,0x3ec4bf80,0x3f6d0000,0xbec43f80,0x3ec43f35,0xbf6d3f35,0xbec4bf35,0x3f6dbf35,
0x3f620000,0xbef13f80,0xbe95bf35,0x3f75bf35,0xbdc9bf55,0x3f7fbf0e,0xbf223f7b,0xbf46be48,0xbf463f6d,0xbf22bec4,0x3f7fbec4,0xbdc93f6d,
0x3f75be48,0xbe953f7b,0xbef1bf0e,0x3f62bf55,0x3f0ebf80,0x3f550000,0xbf550000,0x3f0ebf80,0xbf7b3ec4,0x3e48bf6d,0xbe483f6d,0xbf7b3ec4,
0x3e483f35,0xbf7b3f35,0x3f7bbf35,0x3e483f35,0x3f55bf6d,0x3f0e3ec4,0xbf0ebec4,0x3f55bf6d,0xbf460000,0x3f22bf80,0xbf7f3f35,0xbdc9bf35,
0xbef13f7b,0xbf623e48,0x3e953f0e,0xbf753f55,0x3f75bec4,0xbe953f6d,0x3f62bf6d,0x3ef13ec4,0x3dc9bf55,0x3f7fbf0e,0xbf22be48,0x3f46bf7b,
0xbf353f80,0xbf350000,0xbf353f80,0xbf350000,0x3f350000,0xbf353f80,0x3f350000,0xbf353f80,0x3f35bf80,0x3f350000,0x3f35bf80,0x3f350000,
0xbf350000,0x3f35bf80,0xbf350000,0x3f35bf80,0x3f220000,0xbf463f80,0xbdc93f35,0xbf7f3f35,0x3f62bf7b,0x3ef13e48,0x3f75bf0e,0xbe953f55,
0xbe95bec4,0x3f75bf6d,0x3ef1bf6d,0x3f62bec4,0xbf7f3f55,0xbdc9bf0e,0xbf463e48,0x3f22bf7b,0x3f55bf80,0x3f0e0000,0x3f0e0000,0xbf553f80,
0xbe48bec4,0x3f7bbf6d,0x3f7bbf6d,0x3e483ec4,0xbf7b3f35,0x3e48bf35,0x3e48bf35,0x3f7bbf35,0xbf0e3f6d,0xbf553ec4,0xbf553ec4,0x3f0ebf6d,
0xbef10000,0x3f62bf80,0x3f75bf35,0xbe953f35,0xbf7f3f55,0x3dc9bf0e,0x3f46bf7b,0x3f22be48,0xbf223f6d,0xbf463ec4,0xbdc9bec4,0x3f7fbf6d,
0x3e953e48,0xbf753f7b,0xbf623f0e,0x3ef1bf55,0xbf6d3f80,0xbec40000,0x3f6dbf80,0x3ec40000,0xbec43f35,0xbf6d3f35,0x3ec4bf35,0x3f6dbf35,
0x3ec40000,0xbf6d3f80,0xbec40000,0x3f6dbf80,0x3f6dbf35,0xbec43f35,0xbf6d3f35,0x3ec4bf35,0x3e950000,0xbf753f80,0x3ef1bf35,0x3f62bf35,
0x3f46bf0e,0xbf223f55,0xbdc9be48,0x3f7fbf7b,0x3f7fbf6d,0xbdc93ec4,0xbf223ec4,0x3f46bf6d,0x3f62bf7b,0x3ef1be48,0xbf753f55,0x3e95bf0e,
0x3f7bbf80,0x3e480000,0xbe480000,0x3f7bbf80,0x3f55bf6d,0x3f0ebec4,0xbf0e3ec4,0x3f55bf6d,0x3f0ebf35,0x3f55bf35,0xbf553f35,0x3f0ebf35,
0x3e48bec4,0x3f7bbf6d,0xbf7b3f6d,0x3e48bec4,0xbdc90000,0x3f7fbf80,0xbf463f35,0x3f22bf35,0xbe953e48,0x3f75bf7b,0xbf623f55,0x3ef1bf0e,
0xbef13ec4,0x3f62bf6d,0xbf753f6d,0x3e95bec4,0xbf223f0e,0x3f46bf55,0xbf7f3f7b,0x3dc9be48,0x40003f80,0x3fb53f80,0x3f80,0xbfb53f80,
0x40004000,0xbfb50000,0x0,0xbfb5c000,0x40004000,0xbfb5c000,0x0,0x3fb50000,0x40004000,0x3fb50000,0x0,0x3fb54000,
0x3fff3f80,0x3fa23f80,0xbe49bf80,0xbfc6bf80,0x3ff53ffb,0xbfe2bec8,0xbf15bec8,0xbf71bffb,0x3fe23fed,0xbf15bfed,0xbf71bf44,0x3ff53f44,
0x3fc63fd5,0x3fff3f8e,0xbfa2bf8e,0x3e493fd5,0x3ffb3f80,0x3f8e3f80,0xbec83f80,0xbfd53f80,0x3fd53fed,0xbffbbf44,0xbf8ebf44,0xbec8bfed,
0x3f8e3fb5,0x3ec8bfb5,0xbfd5bfb5,0x3ffb3fb5,0x3ec83f44,0x3fd53fed,0xbffbbfed,0xbf8e3f44,0x3ff53f80,0x3f713f80,0xbf15bf80,0xbfe2bf80,
0x3fa23fd5,0xbfffbf8e,0xbfc6bf8e,0x3e49bfd5,0x3e493f44,0x3fa2bf44,0xbfffbfed,0x3fc63fed,0xbf71bec8,0x3f153ffb,0xbfe2bffb,0xbff5bec8,
0x3fed3f80,0x3f443f80,0xbf443f80,0xbfed3f80,0x3f443fb5,0xbfedbfb5,0xbfedbfb5,0x3f44bfb5,0xbf440000,0x3fed0000,0xbfedc000,0x3f444000,
0xbfedbfb5,0xbf443fb5,0xbf44bfb5,0xbfedbfb5,0x3fe23f80,0x3f153f80,0xbf71bf80,0xbff5bf80,0x3e493f8e,0xbfc6bfd5,0xbfffbfd5,0x3fa2bf8e,
0xbfc6bf44,0x3fff3f44,0xbfa2bfed,0xbe493fed,0xbff5bffb,0xbfe23ec8,0x3f15bec8,0xbf71bffb,0x3fd53f80,0x3ec83f80,0xbf8e3f80,0xbffb3f80,
0xbec83f44,0xbf8ebfed,0xbffbbfed,0x3fd5bf44,0xbffbbfb5,0x3fd53fb5,0xbec8bfb5,0xbf8e3fb5,0xbf8ebfed,0xbffbbf44,0x3fd53f44,0x3ec8bfed,
0x3fc63f80,0x3e493f80,0xbfa2bf80,0xbfffbf80,0xbf713ec8,0xbf15bffb,0xbfe2bffb,0x3ff5bec8,0xbff5bfed,0x3f713fed,0x3f15bf44,0xbfe23f44,
0x3e49bf8e,0xbfa2bfd5,0x3fff3fd5,0x3fc6bf8e,0x3f80,0xbfb53f80,0xc0003f80,0xbfb53f80,0xc000,0x3fb50000,0x40000000,0xbfb54000,
0x4000,0x3fb5c000,0xc0000000,0x3fb50000,0xc000,0xbfb50000,0x40000000,0x3fb5c000,0xbe493f80,0xbfc63f80,0xbfffbf80,0xbfa2bf80,
0x3f15bffb,0x3f713ec8,0x3ff53ec8,0xbfe23ffb,0xbf713fed,0x3ff5bfed,0xbfe2bf44,0x3f153f44,0x3fa2bfd5,0xbe49bf8e,0x3fc63f8e,0x3fffbfd5,
0xbec83f80,0xbfd53f80,0xbffb3f80,0xbf8e3f80,0x3f8ebfed,0x3ec83f44,0x3fd53f44,0xbffb3fed,0xbfd53fb5,0x3ffbbfb5,0xbf8ebfb5,0xbec83fb5,
0x3ffbbf44,0x3f8ebfed,0x3ec83fed,0x3fd5bf44,0xbf153f80,0xbfe23f80,0xbff5bf80,0xbf71bf80,0x3fc6bfd5,0xbe493f8e,0x3fa23f8e,0xbfff3fd5,
0xbfff3f44,0x3fc6bf44,0xbe49bfed,0xbfa23fed,0x3fe23ec8,0x3ff5bffb,0xbf713ffb,0x3f153ec8,0xbf443f80,0xbfed3f80,0xbfed3f80,0xbf443f80,
0x3fedbfb5,0xbf443fb5,0x3f443fb5,0xbfed3fb5,0xbfed0000,0x3f440000,0x3f44c000,0xbfed4000,0x3f443fb5,0x3fedbfb5,0xbfed3fb5,0xbf443fb5,
0xbf713f80,0xbff53f80,0xbfe2bf80,0xbf15bf80,0x3fffbf8e,0xbfa23fd5,0x3e493fd5,0xbfc63f8e,0xbfa2bf44,0xbe493f44,0x3fc6bfed,0xbfff3fed,
0xbf153ffb,0x3f71bec8,0xbff53ec8,0xbfe23ffb,0xbf8e3f80,0xbffb3f80,0xbfd53f80,0xbec83f80,0x3ffbbf44,0xbfd53fed,0xbec83fed,0xbf8e3f44,
0xbec8bfb5,0xbf8e3fb5,0x3ffbbfb5,0xbfd53fb5,0xbfd53fed,0xbec83f44,0xbf8ebf44,0xbffb3fed,0xbfa23f80,0xbfff3f80,0xbfc6bf80,0xbe49bf80,
0x3fe2bec8,0xbff53ffb,0xbf713ffb,0xbf153ec8,0x3f15bfed,0xbfe23fed,0x3ff5bf44,0xbf713f44,0xbfff3f8e,0xbfc63fd5,0x3e49bfd5,0xbfa23f8e,
0xc0003f80,0xbfb53f80,0x3f80,0x3fb53f80,0xc0004000,0x3fb50000,0x0,0x3fb5c000,0xc0004000,0x3fb5c000,0x0,0xbfb50000,
0xc0004000,0xbfb50000,0x0,0xbfb54000,0xbfff3f80,0xbfa23f80,0x3e49bf80,0x3fc6bf80,0xbff53ffb,0x3fe2bec8,0x3f15bec8,0x3f71bffb,
0xbfe23fed,0x3f15bfed,0x3f71bf44,0xbff53f44,0xbfc63fd5,0xbfff3f8e,0x3fa2bf8e,0xbe493fd5,0xbffb3f80,0xbf8e3f80,0x3ec83f80,0x3fd53f80,
0xbfd53fed,0x3ffbbf44,0x3f8ebf44,0x3ec8bfed,0xbf8e3fb5,0xbec8bfb5,0x3fd5bfb5,0xbffb3fb5,0xbec83f44,0xbfd53fed,0x3ffbbfed,0x3f8e3f44,
0xbff53f80,0xbf713f80,0x3f15bf80,0x3fe2bf80,0xbfa23fd5,0x3fffbf8e,0x3fc6bf8e,0xbe49bfd5,0xbe493f44,0xbfa2bf44,0x3fffbfed,0xbfc63fed,
0x3f71bec8,0xbf153ffb,0x3fe2bffb,0x3ff5bec8,0xbfed3f80,0xbf443f80,0x3f443f80,0x3fed3f80,0xbf443fb5,0x3fedbfb5,0x3fedbfb5,0xbf44bfb5,
0x3f440000,0xbfed0000,0x3fedc000,0xbf444000,0x3fedbfb5,0x3f443fb5,0x3f44bfb5,0x3fedbfb5,0xbfe23f80,0xbf153f80,0x3f71bf80,0x3ff5bf80,
0xbe493f8e,0x3fc6bfd5,0x3fffbfd5,0xbfa2bf8e,0x3fc6bf44,0xbfff3f44,0x3fa2bfed,0x3e493fed,0x3ff5bffb,0x3fe23ec8,0xbf15bec8,0x3f71bffb,
0xbfd53f80,0xbec83f80,0x3f8e3f80,0x3ffb3f80,0x3ec83f44,0x3f8ebfed,0x3ffbbfed,0xbfd5bf44,0x3ffbbfb5,0xbfd53fb5,0x3ec8bfb5,0x3f8e3fb5,
0x3f8ebfed,0x3ffbbf44,0xbfd53f44,0xbec8bfed,0xbfc63f80,0xbe493f80,0x3fa2bf80,0x3fffbf80,0x3f713ec8,0x3f15bffb,0x3fe2bffb,0xbff5bec8,
0x3ff5bfed,0xbf713fed,0xbf15bf44,0x3fe23f44,0xbe49bf8e,0x3fa2bfd5,0xbfff3fd5,0xbfc6bf8e,0x3f80,0x3fb53f80,0x40003f80,0x3fb53f80,
0xc000,0xbfb50000,0xc0000000,0x3fb54000,0x4000,0xbfb5c000,0x40000000,0xbfb50000,0xc000,0x3fb50000,0xc0000000,0xbfb5c000,
0x3e493f80,0x3fc63f80,0x3fffbf80,0x3fa2bf80,0xbf15bffb,0xbf713ec8,0xbff53ec8,0x3fe23ffb,0x3f713fed,0xbff5bfed,0x3fe2bf44,0xbf153f44,
0xbfa2bfd5,0x3e49bf8e,0xbfc63f8e,0xbfffbfd5,0x3ec83f80,0x3fd53f80,0x3ffb3f80,0x3f8e3f80,0xbf8ebfed,0xbec83f44,0xbfd53f44,0x3ffb3fed,
0x3fd53fb5,0xbffbbfb5,0x3f8ebfb5,0x3ec83fb5,0xbffbbf44,0xbf8ebfed,0xbec83fed,0xbfd5bf44,0x3f153f80,0x3fe23f80,0x3ff5bf80,0x3f71bf80,
0xbfc6bfd5,0x3e493f8e,0xbfa23f8e,0x3fff3fd5,0x3fff3f44,0xbfc6bf44,0x3e49bfed,0x3fa23fed,0xbfe23ec8,0xbff5bffb,0x3f713ffb,0xbf153ec8,
0x3f443f80,0x3fed3f80,0x3fed3f80,0x3f443f80,0xbfedbfb5,0x3f443fb5,0xbf443fb5,0x3fed3fb5,0x3fed0000,0xbf440000,0xbf44c000,0x3fed4000,
0xbf443fb5,0xbfedbfb5,0x3fed3fb5,0x3f443fb5,0x3f713f80,0x3ff53f80,0x3fe2bf80,0x3f15bf80,0xbfffbf8e,0x3fa23fd5,0xbe493fd5,0x3fc63f8e,
0x3fa2bf44,0x3e493f44,0xbfc6bfed,0x3fff3fed,0x3f153ffb,0xbf71bec8,0x3ff53ec8,0x3fe23ffb,0x3f8e3f80,0x3ffb3f80,0x3fd53f80,0x3ec83f80,
0xbffbbf44,0x3fd53fed,0x3ec83fed,0x3f8e3f44,0x3ec8bfb5,0x3f8e3fb5,0xbffbbfb5,0x3fd53fb5,0x3fd53fed,0x3ec83f44,0x3f8ebf44,0x3ffb3fed,
0x3fa23f80,0x3fff3f80,0x3fc6bf80,0x3e49bf80,0xbfe2bec8,0x3ff53ffb,0x3f713ffb,0x3f153ec8,0xbf15bfed,0x3fe23fed,0xbff5bf44,0x3f713f44,
0x3fff3f8e,0x3fc63fd5,0xbe49bfd5,0x3fa23f8e,0x40004000,0x3fb54000,0x0,0xbfb50000,0x40004000,0xbfb50000,0x0,0xbfb5c000,
0x40004000,0xbfb5c000,0x0,0x3fb50000,0x40004000,0x3fb50000,0x0,0x3fb54000,0x3fa23fb5,0xbe493fb5,0xbfc6bfb5,0xbfffbfb5,
0x3f713f8e,0xbff5bfd5,0xbfe2bfd5,0x3f15bf8e,0x3f153f44,0x3f71bf44,0xbff5bfed,0x3fe23fed,0x3e493ec8,0x3fc63ffb,0xbfffbffb,0xbfa23ec8,
0xbec80000,0xbfd50000,0xbffbc000,0xbf8ec000,0xbf8ebf44,0xbec8bfed,0xbfd5bfed,0x3ffb3f44,0xbfd5bfb5,0x3ffb3fb5,0xbf8ebfb5,0xbec83fb5,
0xbffbbfed,0xbf8e3f44,0xbec8bf44,0xbfd5bfed,0xbfe2bfb5,0xbff5bfb5,0xbf71bfb5,0x3f15bfb5,0xbfffbffb,0x3fc6bec8,0x3e49bec8,0x3fa23ffb,
0xbfc6bfed,0x3e493fed,0x3fa23f44,0xbfffbf44,0xbf15bf8e,0xbfe2bfd5,0x3ff53fd5,0x3f71bf8e,0xbfedc000,0xbf44c000,0x3f440000,0x3fed0000,
0xbf44bfb5,0x3fed3fb5,0x3fed3fb5,0xbf443fb5,0x3f440000,0xbfed0000,0x3fed4000,0xbf44c000,0x3fed3fb5,0x3f44bfb5,0x3f443fb5,0x3fed3fb5,
0xbf15bfb5,0x3f71bfb5,0x3ff53fb5,0x3fe23fb5,0x3fa23ec8,0x3e493ffb,0x3fc63ffb,0xbfffbec8,0x3fff3fed,0xbfa2bfed,0xbe493f44,0x3fc6bf44,
0x3f713fd5,0x3ff53f8e,0xbfe2bf8e,0xbf153fd5,0x3f8e0000,0x3ffb0000,0x3fd54000,0x3ec84000,0x3ffb3fed,0xbfd53f44,0xbec83f44,0xbf8ebfed,
0x3ec83fb5,0x3f8ebfb5,0xbffbbfb5,0x3fd53fb5,0xbfd5bf44,0xbec83fed,0xbf8ebfed,0xbffbbf44,0x3fff3fb5,0x3fc63fb5,0x3e493fb5,0xbfa23fb5,
0x3f153fd5,0xbfe2bf8e,0xbff5bf8e,0x3f71bfd5,0xbfe2bf44,0x3ff53f44,0xbf71bfed,0xbf153fed,0xbfa2bffb,0xbfffbec8,0x3fc63ec8,0x3e49bffb,
0x4000,0xbfb54000,0xc0000000,0xbfb50000,0xc000,0x3fb50000,0x40000000,0xbfb54000,0x4000,0x3fb5c000,0xc0000000,0x3fb50000,
0xc000,0xbfb50000,0x40000000,0x3fb5c000,0xbfc63fb5,0xbfff3fb5,0xbfa2bfb5,0x3e49bfb5,0x3fe2bf8e,0xbf153fd5,0x3f713fd5,0xbff53f8e,
0xbff53f44,0x3fe2bf44,0xbf15bfed,0xbf713fed,0x3fffbec8,0x3fa2bffb,0x3e493ffb,0x3fc6bec8,0xbffb0000,0xbf8e0000,0x3ec8c000,0x3fd5c000,
0x3fd53f44,0xbffb3fed,0xbf8e3fed,0xbec8bf44,0xbf8ebfb5,0xbec83fb5,0x3fd5bfb5,0xbffb3fb5,0x3ec83fed,0x3fd5bf44,0xbffb3f44,0xbf8e3fed,
0xbf71bfb5,0x3f15bfb5,0x3fe2bfb5,0x3ff5bfb5,0xbe493ffb,0xbfa23ec8,0xbfff3ec8,0x3fc6bffb,0x3fa2bfed,0xbfff3fed,0x3fc63f44,0xbe49bf44,
0xbff53f8e,0xbf713fd5,0xbf15bfd5,0xbfe23f8e,0x3f44c000,0x3fedc000,0x3fed0000,0x3f440000,0xbfed3fb5,0x3f44bfb5,0xbf44bfb5,0x3fedbfb5,
0x3fed0000,0xbf440000,0xbf444000,0x3fedc000,0xbf44bfb5,0xbfed3fb5,0x3fedbfb5,0x3f44bfb5,0x3ff5bfb5,0x3fe2bfb5,0x3f153fb5,0xbf713fb5,
0xbfc6bec8,0x3fffbffb,0x3fa2bffb,0x3e493ec8,0xbe493fed,0x3fc6bfed,0xbfff3f44,0x3fa2bf44,0x3fe2bfd5,0x3f15bf8e,0x3f713f8e,0x3ff5bfd5,
0x3fd50000,0x3ec80000,0xbf8e4000,0xbffb4000,0x3ec8bfed,0x3f8ebf44,0x3ffbbf44,0xbfd53fed,0xbffb3fb5,0x3fd5bfb5,0xbec8bfb5,0xbf8e3fb5,
0x3f8e3f44,0x3ffbbfed,0xbfd53fed,0xbec83f44,0x3e493fb5,0xbfa23fb5,0xbfff3fb5,0xbfc63fb5,0x3ff5bfd5,0xbf713f8e,0x3f153f8e,0xbfe23fd5,
0xbf71bf44,0xbf153f44,0x3fe2bfed,0xbff53fed,0xbfc63ffb,0xbe493ec8,0xbfa2bec8,0xbfff3ffb,0xc0004000,0xbfb54000,0x0,0x3fb50000,
0xc0004000,0x3fb50000,0x0,0x3fb5c000,0xc0004000,0x3fb5c000,0x0,0xbfb50000,0xc0004000,0xbfb50000,0x0,0xbfb54000,
0xbfa23fb5,0x3e493fb5,0x3fc6bfb5,0x3fffbfb5,0xbf713f8e,0x3ff5bfd5,0x3fe2bfd5,0xbf15bf8e,0xbf153f44,0xbf71bf44,0x3ff5bfed,0xbfe23fed,
0xbe493ec8,0xbfc63ffb,0x3fffbffb,0x3fa23ec8,0x3ec80000,0x3fd50000,0x3ffbc000,0x3f8ec000,0x3f8ebf44,0x3ec8bfed,0x3fd5bfed,0xbffb3f44,
0x3fd5bfb5,0xbffb3fb5,0x3f8ebfb5,0x3ec83fb5,0x3ffbbfed,0x3f8e3f44,0x3ec8bf44,0x3fd5bfed,0x3fe2bfb5,0x3ff5bfb5,0x3f71bfb5,0xbf15bfb5,
0x3fffbffb,0xbfc6bec8,0xbe49bec8,0xbfa23ffb,0x3fc6bfed,0xbe493fed,0xbfa23f44,0x3fffbf44,0x3f15bf8e,0x3fe2bfd5,0xbff53fd5,0xbf71bf8e,
0x3fedc000,0x3f44c000,0xbf440000,0xbfed0000,0x3f44bfb5,0xbfed3fb5,0xbfed3fb5,0x3f443fb5,0xbf440000,0x3fed0000,0xbfed4000,0x3f44c000,
0xbfed3fb5,0xbf44bfb5,0xbf443fb5,0xbfed3fb5,0x3f15bfb5,0xbf71bfb5,0xbff53fb5,0xbfe23fb5,0xbfa23ec8,0xbe493ffb,0xbfc63ffb,0x3fffbec8,
0xbfff3fed,0x3fa2bfed,0x3e493f44,0xbfc6bf44,0xbf713fd5,0xbff53f8e,0x3fe2bf8e,0x3f153fd5,0xbf8e0000,0xbffb0000,0xbfd54000,0xbec84000,
0xbffb3fed,0x3fd53f44,0x3ec83f44,0x3f8ebfed,0xbec83fb5,0xbf8ebfb5,0x3ffbbfb5,0xbfd53fb5,0x3fd5bf44,0x3ec83fed,0x3f8ebfed,0x3ffbbf44,
0xbfff3fb5,0xbfc63fb5,0xbe493fb5,0x3fa23fb5,0xbf153fd5,0x3fe2bf8e,0x3ff5bf8e,0xbf71bfd5,0x3fe2bf44,0xbff53f44,0x3f71bfed,0x3f153fed,
0x3fa2bffb,0x3fffbec8,0xbfc63ec8,0xbe49bffb,0x4000,0x3fb54000,0x40000000,0x3fb50000,0xc000,0xbfb50000,0xc0000000,0x3fb54000,
0x4000,0xbfb5c000,0x40000000,0xbfb50000,0xc000,0x3fb50000,0xc0000000,0xbfb5c000,0x3fc63fb5,0x3fff3fb5,0x3fa2bfb5,0xbe49bfb5,
0xbfe2bf8e,0x3f153fd5,0xbf713fd5,0x3ff53f8e,0x3ff53f44,0xbfe2bf44,0x3f15bfed,0x3f713fed,0xbfffbec8,0xbfa2bffb,0xbe493ffb,0xbfc6bec8,
0x3ffb0000,0x3f8e0000,0xbec8c000,0xbfd5c000,0xbfd53f44,0x3ffb3fed,0x3f8e3fed,0x3ec8bf44,0x3f8ebfb5,0x3ec83fb5,0xbfd5bfb5,0x3ffb3fb5,
0xbec83fed,0xbfd5bf44,0x3ffb3f44,0x3f8e3fed,0x3f71bfb5,0xbf15bfb5,0xbfe2bfb5,0xbff5bfb5,0x3e493ffb,0x3fa23ec8,0x3fff3ec8,0xbfc6bffb,
0xbfa2bfed,0x3fff3fed,0xbfc63f44,0x3e49bf44,0x3ff53f8e,0x3f713fd5,0x3f15bfd5,0x3fe23f8e,0xbf44c000,0xbfedc000,0xbfed0000,0xbf440000,
0x3fed3fb5,0xbf44bfb5,0x3f44bfb5,0xbfedbfb5,0xbfed0000,0x3f440000,0x3f444000,0xbfedc000,0x3f44bfb5,0x3fed3fb5,0xbfedbfb5,0xbf44bfb5,
0xbff5bfb5,0xbfe2bfb5,0xbf153fb5,0x3f713fb5,0x3fc6bec8,0xbfffbffb,0xbfa2bffb,0xbe493ec8,0x3e493fed,0xbfc6bfed,0x3fff3f44,0xbfa2bf44,
0xbfe2bfd5,0xbf15bf8e,0xbf713f8e,0xbff5bfd5,0xbfd50000,0xbec80000,0x3f8e4000,0x3ffb4000,0xbec8bfed,0xbf8ebf44,0xbffbbf44,0x3fd53fed,
0x3ffb3fb5,0xbfd5bfb5,0x3ec8bfb5,0x3f8e3fb5,0xbf8e3f44,0xbffbbfed,0x3fd53fed,0x3ec83f44,0xbe493fb5,0x3fa23fb5,0x3fff3fb5,0x3fc63fb5,
0xbff5bfd5,0x3f713f8e,0xbf153f8e,0x3fe23fd5,0x3f71bf44,0x3f153f44,0xbfe2bfed,0x3ff53fed,0x3fc63ffb,0x3e493ec8,0x3fa2bec8,0x3fff3ffb,
0x40004000,0x3fb54000,0x0,0xbfb50000,0x40004000,0xbfb50000,0x0,0xbfb5c000,0x40004000,0xbfb5c000,0x0,0x3fb50000,
0x40004000,0x3fb50000,0x0,0x3fb54000,0xbe490000,0xbfc60000,0xbfffc000,0xbfa2c000,0xbf15bec8,0xbf71bffb,0xbff5bffb,0x3fe23ec8,
0xbf71bf44,0x3ff53f44,0xbfe2bfed,0x3f153fed,0xbfa2bf8e,0x3e493fd5,0xbfc6bfd5,0xbfffbf8e,0xbffbc000,0xbf8ec000,0x3ec80000,0x3fd50000,
0xbfd5bfed,0x3ffb3f44,0x3f8e3f44,0x3ec83fed,0xbf8ebfb5,0xbec83fb5,0x3fd53fb5,0xbffbbfb5,0xbec8bf44,0xbfd5bfed,0x3ffb3fed,0x3f8ebf44,
0x3f150000,0x3fe20000,0x3ff54000,0x3f714000,0x3fc63f8e,0xbe493fd5,0x3fa23fd5,0xbfffbf8e,0x3fff3fed,0xbfc6bfed,0x3e493f44,0x3fa2bf44,
0x3fe23ffb,0x3ff53ec8,0xbf71bec8,0x3f153ffb,0x3fed4000,0x3f444000,0xbf440000,0xbfed0000,0x3f443fb5,0xbfedbfb5,0xbfedbfb5,0x3f44bfb5,
0xbf440000,0x3fed0000,0xbfedc000,0x3f444000,0xbfedbfb5,0xbf443fb5,0xbf44bfb5,0xbfedbfb5,0xbf710000,0xbff50000,0xbfe2c000,0xbf15c000,
0xbfffbfd5,0x3fa2bf8e,0xbe49bf8e,0x3fc63fd5,0xbfa2bfed,0xbe493fed,0x3fc63f44,0xbfffbf44,0x3f15bec8,0xbf71bffb,0x3ff53ffb,0x3fe2bec8,
0xbfd5c000,0xbec8c000,0x3f8e0000,0x3ffb0000,0x3ec8bf44,0x3f8e3fed,0x3ffb3fed,0xbfd53f44,0x3ffb3fb5,0xbfd5bfb5,0x3ec83fb5,0x3f8ebfb5,
0x3f8e3fed,0x3ffb3f44,0xbfd5bf44,0xbec83fed,0x3fa20000,0x3fff0000,0x3fc64000,0x3e494000,0x3fe23ffb,0xbff53ec8,0xbf713ec8,0xbf15bffb,
0xbf153f44,0x3fe2bf44,0xbff5bfed,0x3f713fed,0xbfffbfd5,0xbfc63f8e,0x3e49bf8e,0xbfa2bfd5,0x4000,0xbfb54000,0xc0000000,0xbfb50000,
0xc000,0x3fb50000,0x40000000,0xbfb54000,0x4000,0x3fb5c000,0xc0000000,0x3fb50000,0xc000,0xbfb50000,0x40000000,0x3fb5c000,
0xbfff0000,0xbfa20000,0x3e49c000,0x3fc6c000,0x3ff53ec8,0xbfe23ffb,0xbf153ffb,0xbf71bec8,0xbfe2bf44,0x3f153f44,0x3f71bfed,0xbff53fed,
0x3fc63f8e,0x3fffbfd5,0xbfa23fd5,0x3e493f8e,0x3ec8c000,0x3fd5c000,0x3ffb0000,0x3f8e0000,0xbf8e3fed,0xbec8bf44,0xbfd5bf44,0x3ffbbfed,
0x3fd5bfb5,0xbffb3fb5,0x3f8e3fb5,0x3ec8bfb5,0xbffb3f44,0xbf8e3fed,0xbec8bfed,0xbfd53f44,0x3ff50000,0x3f710000,0xbf154000,0xbfe24000,
0xbfa2bf8e,0x3fffbfd5,0x3fc6bfd5,0xbe493f8e,0x3e493fed,0x3fa2bfed,0xbfff3f44,0x3fc6bf44,0x3f71bffb,0xbf15bec8,0x3fe23ec8,0x3ff5bffb,
0xbf444000,0xbfed4000,0xbfed0000,0xbf440000,0x3fedbfb5,0xbf443fb5,0x3f443fb5,0xbfed3fb5,0xbfed0000,0x3f440000,0x3f44c000,0xbfed4000,
0x3f443fb5,0x3fedbfb5,0xbfed3fb5,0xbf443fb5,0xbfe20000,0xbf150000,0x3f71c000,0x3ff5c000,0x3e493fd5,0xbfc63f8e,0xbfff3f8e,0x3fa2bfd5,
0x3fc6bfed,0xbfff3fed,0x3fa23f44,0x3e49bf44,0xbff53ec8,0xbfe23ffb,0x3f15bffb,0xbf713ec8,0x3f8ec000,0x3ffbc000,0x3fd50000,0x3ec80000,
0xbffb3f44,0x3fd5bfed,0x3ec8bfed,0x3f8ebf44,0x3ec83fb5,0x3f8ebfb5,0xbffb3fb5,0x3fd5bfb5,0x3fd5bfed,0x3ec8bf44,0x3f8e3f44,0x3ffbbfed,
0x3fc60000,0x3e490000,0xbfa24000,0xbfff4000,0x3f71bffb,0x3f15bec8,0x3fe2bec8,0xbff53ffb,0xbff53f44,0x3f71bf44,0x3f15bfed,0xbfe23fed,
0xbe493fd5,0x3fa2bf8e,0xbfff3f8e,0xbfc63fd5,0xc0004000,0xbfb54000,0x0,0x3fb50000,0xc0004000,0x3fb50000,0x0,0x3fb5c000,
0xc0004000,0x3fb5c000,0x0,0xbfb50000,0xc0004000,0xbfb50000,0x0,0xbfb54000,0x3e490000,0x3fc60000,0x3fffc000,0x3fa2c000,
0x3f15bec8,0x3f71bffb,0x3ff5bffb,0xbfe23ec8,0x3f71bf44,0xbff53f44,0x3fe2bfed,0xbf153fed,0x3fa2bf8e,0xbe493fd5,0x3fc6bfd5,0x3fffbf8e,
0x3ffbc000,0x3f8ec000,0xbec80000,0xbfd50000,0x3fd5bfed,0xbffb3f44,0xbf8e3f44,0xbec83fed,0x3f8ebfb5,0x3ec83fb5,0xbfd53fb5,0x3ffbbfb5,
0x3ec8bf44,0x3fd5bfed,0xbffb3fed,0xbf8ebf44,0xbf150000,0xbfe20000,0xbff54000,0xbf714000,0xbfc63f8e,0x3e493fd5,0xbfa23fd5,0x3fffbf8e,
0xbfff3fed,0x3fc6bfed,0xbe493f44,0xbfa2bf44,0xbfe23ffb,0xbff53ec8,0x3f71bec8,0xbf153ffb,0xbfed4000,0xbf444000,0x3f440000,0x3fed0000,
0xbf443fb5,0x3fedbfb5,0x3fedbfb5,0xbf44bfb5,0x3f440000,0xbfed0000,0x3fedc000,0xbf444000,0x3fedbfb5,0x3f443fb5,0x3f44bfb5,0x3fedbfb5,
0x3f710000,0x3ff50000,0x3fe2c000,0x3f15c000,0x3fffbfd5,0xbfa2bf8e,0x3e49bf8e,0xbfc63fd5,0x3fa2bfed,0x3e493fed,0xbfc63f44,0x3fffbf44,
0xbf15bec8,0x3f71bffb,0xbff53ffb,0xbfe2bec8,0x3fd5c000,0x3ec8c000,0xbf8e0000,0xbffb0000,0xbec8bf44,0xbf8e3fed,0xbffb3fed,0x3fd53f44,
0xbffb3fb5,0x3fd5bfb5,0xbec83fb5,0xbf8ebfb5,0xbf8e3fed,0xbffb3f44,0x3fd5bf44,0x3ec83fed,0xbfa20000,0xbfff0000,0xbfc64000,0xbe494000,
0xbfe23ffb,0x3ff53ec8,0x3f713ec8,0x3f15bffb,0x3f153f44,0xbfe2bf44,0x3ff5bfed,0xbf713fed,0x3fffbfd5,0x3fc63f8e,0xbe49bf8e,0x3fa2bfd5,
0x4000,0x3fb54000,0x40000000,0x3fb50000,0xc000,0xbfb50000,0xc0000000,0x3fb54000,0x4000,0xbfb5c000,0x40000000,0xbfb50000,
0xc000,0x3fb50000,0xc0000000,0xbfb5c000,0x3fff0000,0x3fa20000,0xbe49c000,0xbfc6c000,0xbff53ec8,0x3fe23ffb,0x3f153ffb,0x3f71bec8,
0x3fe2bf44,0xbf153f44,0xbf71bfed,0x3ff53fed,0xbfc63f8e,0xbfffbfd5,0x3fa23fd5,0xbe493f8e,0xbec8c000,0xbfd5c000,0xbffb0000,0xbf8e0000,
0x3f8e3fed,0x3ec8bf44,0x3fd5bf44,0xbffbbfed,0xbfd5bfb5,0x3ffb3fb5,0xbf8e3fb5,0xbec8bfb5,0x3ffb3f44,0x3f8e3fed,0x3ec8bfed,0x3fd53f44,
0xbff50000,0xbf710000,0x3f154000,0x3fe24000,0x3fa2bf8e,0xbfffbfd5,0xbfc6bfd5,0x3e493f8e,0xbe493fed,0xbfa2bfed,0x3fff3f44,0xbfc6bf44,
0xbf71bffb,0x3f15bec8,0xbfe23ec8,0xbff5bffb,0x3f444000,0x3fed4000,0x3fed0000,0x3f440000,0xbfedbfb5,0x3f443fb5,0xbf443fb5,0x3fed3fb5,
0x3fed0000,0xbf440000,0xbf44c000,0x3fed4000,0xbf443fb5,0xbfedbfb5,0x3fed3fb5,0x3f443fb5,0x3fe20000,0x3f150000,0xbf71c000,0xbff5c000,
0xbe493fd5,0x3fc63f8e,0x3fff3f8e,0xbfa2bfd5,0xbfc6bfed,0x3fff3fed,0xbfa23f44,0xbe49bf44,0x3ff53ec8,0x3fe23ffb,0xbf15bffb,0x3f713ec8,
0xbf8ec000,0xbffbc000,0xbfd50000,0xbec80000,0x3ffb3f44,0xbfd5bfed,0xbec8bfed,0xbf8ebf44,0xbec83fb5,0xbf8ebfb5,0x3ffb3fb5,0xbfd5bfb5,
0xbfd5bfed,0xbec8bf44,0xbf8e3f44,0xbffbbfed,0xbfc60000,0xbe490000,0x3fa24000,0x3fff4000,0xbf71bffb,0xbf15bec8,0xbfe2bec8,0x3ff53ffb,
0x3ff53f44,0xbf71bf44,0xbf15bfed,0x3fe23fed,0x3e493fd5,0xbfa2bf8e,0x3fff3f8e,0x3fc63fd5,0x40004000,0x3fb54000,0x0,0xbfb50000,
0x40004000,0xbfb50000,0x0,0xbfb5c000,0x40004000,0xbfb5c000,0x0,0x3fb50000,0x40004000,0x3fb50000,0x0,0x3fb54000,
0xbfc6bfb5,0xbfffbfb5,0xbfa2bfb5,0x3e49bfb5,0xbfe2bfd5,0x3f15bf8e,0xbf71bf8e,0x3ff53fd5,0xbff5bfed,0x3fe23fed,0xbf15bf44,0xbf713f44,
0xbfffbffb,0xbfa23ec8,0xbe49bec8,0xbfc6bffb,0x3ec80000,0x3fd50000,0x3ffb4000,0x3f8e4000,0x3f8e3f44,0x3ec83fed,0x3fd53fed,0xbffbbf44,
0x3fd53fb5,0xbffbbfb5,0x3f8e3fb5,0x3ec8bfb5,0x3ffb3fed,0x3f8ebf44,0x3ec83f44,0x3fd53fed,0x3f713fb5,0xbf153fb5,0xbfe2bfb5,0xbff5bfb5,
0xbe493ec8,0xbfa2bffb,0xbfffbffb,0x3fc6bec8,0xbfa2bf44,0x3fff3f44,0xbfc6bfed,0x3e493fed,0xbff5bfd5,0xbf713f8e,0xbf15bf8e,0xbfe2bfd5,
0xbfedc000,0xbf44c000,0x3f440000,0x3fed0000,0xbf44bfb5,0x3fed3fb5,0x3fed3fb5,0xbf443fb5,0x3f440000,0xbfed0000,0x3fed4000,0xbf44c000,
0x3fed3fb5,0x3f44bfb5,0x3f443fb5,0x3fed3fb5,0x3ff53fb5,0x3fe23fb5,0x3f153fb5,0xbf713fb5,0x3fc63ffb,0xbfffbec8,0xbfa2bec8,0xbe49bffb,
0xbe493f44,0x3fc6bf44,0xbfffbfed,0x3fa23fed,0xbfe2bf8e,0xbf153fd5,0xbf71bfd5,0xbff5bf8e,0xbf8e0000,0xbffb0000,0xbfd5c000,0xbec8c000,
0xbffbbfed,0x3fd5bf44,0x3ec8bf44,0x3f8e3fed,0xbec8bfb5,0xbf8e3fb5,0x3ffb3fb5,0xbfd5bfb5,0x3fd53f44,0x3ec8bfed,0x3f8e3fed,0x3ffb3f44,
0xbe49bfb5,0x3fa2bfb5,0x3fff3fb5,0x3fc63fb5,0x3ff53f8e,0xbf713fd5,0x3f153fd5,0xbfe2bf8e,0x3f713fed,0x3f15bfed,0xbfe2bf44,0x3ff53f44,
0xbfc6bec8,0xbe493ffb,0xbfa2bffb,0xbfffbec8,0x4000,0xbfb54000,0xc0000000,0xbfb50000,0xc000,0x3fb50000,0x40000000,0xbfb54000,
0x4000,0x3fb5c000,0xc0000000,0x3fb50000,0xc000,0xbfb50000,0x40000000,0x3fb5c000,0xbfa2bfb5,0x3e49bfb5,0x3fc6bfb5,0x3fffbfb5,
0x3f713fd5,0xbff53f8e,0xbfe23f8e,0x3f15bfd5,0xbf15bfed,0xbf713fed,0x3ff5bf44,0xbfe23f44,0x3e493ffb,0x3fc6bec8,0xbfff3ec8,0xbfa23ffb,
0x3ffb0000,0x3f8e0000,0xbec84000,0xbfd54000,0xbfd5bf44,0x3ffbbfed,0x3f8ebfed,0x3ec83f44,0x3f8e3fb5,0x3ec8bfb5,0xbfd53fb5,0x3ffbbfb5,
0xbec8bfed,0xbfd53f44,0x3ffbbf44,0x3f8ebfed,0xbfe23fb5,0xbff53fb5,0xbf71bfb5,0x3f15bfb5,0x3fffbec8,0xbfc63ffb,0xbe493ffb,0xbfa23ec8,
0xbfc6bf44,0x3e493f44,0x3fa2bfed,0xbfff3fed,0x3f153fd5,0x3fe2bf8e,0xbff53f8e,0xbf713fd5,0x3f44c000,0x3fedc000,0x3fed0000,0x3f440000,
0xbfed3fb5,0x3f44bfb5,0xbf44bfb5,0x3fedbfb5,0x3fed0000,0xbf440000,0xbf444000,0x3fedc000,0xbf44bfb5,0xbfed3fb5,0x3fedbfb5,0x3f44bfb5,
0x3f153fb5,0xbf713fb5,0xbff53fb5,0xbfe23fb5,0x3fa2bffb,0x3e493ec8,0x3fc63ec8,0xbfff3ffb,0xbfff3f44,0x3fa2bf44,0x3e49bfed,0xbfc63fed,
0x3f713f8e,0x3ff5bfd5,0xbfe23fd5,0xbf153f8e,0xbfd50000,0xbec80000,0x3f8ec000,0x3ffbc000,0xbec83fed,0xbf8e3f44,0xbffb3f44,0x3fd5bfed,
0x3ffbbfb5,0xbfd53fb5,0x3ec83fb5,0x3f8ebfb5,0xbf8ebf44,0xbffb3fed,0x3fd5bfed,0x3ec8bf44,0x3fffbfb5,0x3fc6bfb5,0x3e493fb5,0xbfa23fb5,
0xbf15bf8e,0x3fe2bfd5,0x3ff5bfd5,0xbf713f8e,0xbfe23fed,0x3ff5bfed,0xbf71bf44,0xbf153f44,0x3fa23ec8,0x3fffbffb,0xbfc63ffb,0xbe493ec8,
0xc0004000,0xbfb54000,0x0,0x3fb50000,0xc0004000,0x3fb50000,0x0,0x3fb5c000,0xc0004000,0x3fb5c000,0x0,0xbfb50000,
0xc0004000,0xbfb50000,0x0,0xbfb54000,0x3fc6bfb5,0x3fffbfb5,0x3fa2bfb5,0xbe49bfb5,0x3fe2bfd5,0xbf15bf8e,0x3f71bf8e,0xbff53fd5,
0x3ff5bfed,0xbfe23fed,0x3f15bf44,0x3f713f44,0x3fffbffb,0x3fa23ec8,0x3e49bec8,0x3fc6bffb,0xbec80000,0xbfd50000,0xbffb4000,0xbf8e4000,
0xbf8e3f44,0xbec83fed,0xbfd53fed,0x3ffbbf44,0xbfd53fb5,0x3ffbbfb5,0xbf8e3fb5,0xbec8bfb5,0xbffb3fed,0xbf8ebf44,0xbec83f44,0xbfd53fed,
0xbf713fb5,0x3f153fb5,0x3fe2bfb5,0x3ff5bfb5,0x3e493ec8,0x3fa2bffb,0x3fffbffb,0xbfc6bec8,0x3fa2bf44,0xbfff3f44,0x3fc6bfed,0xbe493fed,
0x3ff5bfd5,0x3f713f8e,0x3f15bf8e,0x3fe2bfd5,0x3fedc000,0x3f44c000,0xbf440000,0xbfed0000,0x3f44bfb5,0xbfed3fb5,0xbfed3fb5,0x3f443fb5,
0xbf440000,0x3fed0000,0xbfed4000,0x3f44c000,0xbfed3fb5,0xbf44bfb5,0xbf443fb5,0xbfed3fb5,0xbff53fb5,0xbfe23fb5,0xbf153fb5,0x3f713fb5,
0xbfc63ffb,0x3fffbec8,0x3fa2bec8,0x3e49bffb,0x3e493f44,0xbfc6bf44,0x3fffbfed,0xbfa23fed,0x3fe2bf8e,0x3f153fd5,0x3f71bfd5,0x3ff5bf8e,
0x3f8e0000,0x3ffb0000,0x3fd5c000,0x3ec8c000,0x3ffbbfed,0xbfd5bf44,0xbec8bf44,0xbf8e3fed,0x3ec8bfb5,0x3f8e3fb5,0xbffb3fb5,0x3fd5bfb5,
0xbfd53f44,0xbec8bfed,0xbf8e3fed,0xbffb3f44,0x3e49bfb5,0xbfa2bfb5,0xbfff3fb5,0xbfc63fb5,0xbff53f8e,0x3f713fd5,0xbf153fd5,0x3fe2bf8e,
0xbf713fed,0xbf15bfed,0x3fe2bf44,0xbff53f44,0x3fc6bec8,0x3e493ffb,0x3fa2bffb,0x3fffbec8,0x4000,0x3fb54000,0x40000000,0x3fb50000,
0xc000,0xbfb50000,0xc0000000,0x3fb54000,0x4000,0xbfb5c000,0x40000000,0xbfb50000,0xc000,0x3fb50000,0xc0000000,0xbfb5c000,
0x3fa2bfb5,0xbe49bfb5,0xbfc6bfb5,0xbfffbfb5,0xbf713fd5,0x3ff53f8e,0x3fe23f8e,0xbf15bfd5,0x3f15bfed,0x3f713fed,0xbff5bf44,0x3fe23f44,
0xbe493ffb,0xbfc6bec8,0x3fff3ec8,0x3fa23ffb,0xbffb0000,0xbf8e0000,0x3ec84000,0x3fd54000,0x3fd5bf44,0xbffbbfed,0xbf8ebfed,0xbec83f44,
0xbf8e3fb5,0xbec8bfb5,0x3fd53fb5,0xbffbbfb5,0x3ec8bfed,0x3fd53f44,0xbffbbf44,0xbf8ebfed,0x3fe23fb5,0x3ff53fb5,0x3f71bfb5,0xbf15bfb5,
0xbfffbec8,0x3fc63ffb,0x3e493ffb,0x3fa23ec8,0x3fc6bf44,0xbe493f44,0xbfa2bfed,0x3fff3fed,0xbf153fd5,0xbfe2bf8e,0x3ff53f8e,0x3f713fd5,
0xbf44c000,0xbfedc000,0xbfed0000,0xbf440000,0x3fed3fb5,0xbf44bfb5,0x3f44bfb5,0xbfedbfb5,0xbfed0000,0x3f440000,0x3f444000,0xbfedc000,
0x3f44bfb5,0x3fed3fb5,0xbfedbfb5,0xbf44bfb5,0xbf153fb5,0x3f713fb5,0x3ff53fb5,0x3fe23fb5,0xbfa2bffb,0xbe493ec8,0xbfc63ec8,0x3fff3ffb,
0x3fff3f44,0xbfa2bf44,0xbe49bfed,0x3fc63fed,0xbf713f8e,0xbff5bfd5,0x3fe23fd5,0x3f153f8e,0x3fd50000,0x3ec80000,0xbf8ec000,0xbffbc000,
0x3ec83fed,0x3f8e3f44,0x3ffb3f44,0xbfd5bfed,0xbffbbfb5,0x3fd53fb5,0xbec83fb5,0xbf8ebfb5,0x3f8ebf44,0x3ffb3fed,0xbfd5bfed,0xbec8bf44,
0xbfffbfb5,0xbfc6bfb5,0xbe493fb5,0x3fa23fb5,0x3f15bf8e,0xbfe2bfd5,0xbff5bfd5,0x3f713f8e,0x3fe23fed,0xbff5bfed,0x3f71bf44,0x3f153f44,
0xbfa23ec8,0xbfffbffb,0x3fc63ffb,0x3e493ec8,0x80003f80,0x3f800000,0x80003f80,0x3f800000,0x80003f80,0x3f800000,0x80003f80,0x3f800000,
0x80003f80,0x3f800000,0x80003f80,0x3f800000,0x80003f80,0x3f800000,0x80003f80,0x3f800000,0x80003f80,0x3f800000,0x8000bf80,0xbf800000,
0x3f353f35,0x3f35bf35,0xbf35bf35,0xbf353f35,0x3f800000,0xbf80,0xbf800000,0x3f80,0x3f35bf35,0xbf35bf35,0xbf353f35,0x3f353f35,
0x80003f80,0x3f800000,0x80003f80,0x3f800000,0x3f800000,0xbf80,0x3f800000,0xbf80,0x8000bf80,0xbf800000,0x8000bf80,0xbf800000,
0xbf800000,0x3f80,0xbf800000,0x3f80,0x80003f80,0x3f800000,0x8000bf80,0xbf800000,0x3f35bf35,0xbf35bf35,0xbf353f35,0x3f353f35,
0xbf800000,0x3f80,0x3f800000,0xbf80,0x3f353f35,0x3f35bf35,0xbf35bf35,0xbf353f35,0x80003f80,0x3f800000,0x80003f80,0x3f800000,
0x8000bf80,0xbf800000,0x8000bf80,0xbf800000,0x80003f80,0x3f800000,0x80003f80,0x3f800000,0x8000bf80,0xbf800000,0x8000bf80,0xbf800000,
0x80003f80,0x3f800000,0x8000bf80,0xbf800000,0xbf35bf35,0xbf353f35,0x3f353f35,0x3f35bf35,0x3f800000,0xbf80,0xbf800000,0x3f80,
0xbf353f35,0x3f353f35,0x3f35bf35,0xbf35bf35,0x80003f80,0x3f800000,0x80003f80,0x3f800000,0xbf800000,0x3f80,0xbf800000,0x3f80,
0x8000bf80,0xbf800000,0x8000bf80,0xbf800000,0x3f800000,0xbf80,0x3f800000,0xbf80,0x80003f80,0x3f800000,0x8000bf80,0xbf800000,
0xbf353f35,0x3f353f35,0x3f35bf35,0xbf35bf35,0xbf800000,0x3f80,0x3f800000,0xbf80,0xbf35bf35,0xbf353f35,0x3f353f35,0x3f35bf35,
0x3f803f80,0x80008000,0xbf80bf80,0x0,0x3f803f80,0x80008000,0xbf80bf80,0x0,0x3f803f80,0x80008000,0xbf80bf80,0x0,
0x3f803f80,0x80008000,0xbf80bf80,0x0,0x3f353f80,0x3f358000,0xbf35bf80,0x0,0xbf350000,0x3f353f80,0x3f358000,0x0,
0xbf35bf80,0xbf358000,0x3f353f80,0x0,0x3f350000,0xbf35bf80,0xbf358000,0x0,0x3f80,0x3f808000,0x8000bf80,0x0,
0xbf80,0xbf808000,0x80003f80,0x0,0x3f80,0x3f808000,0x8000bf80,0x0,0xbf80,0xbf808000,0x80003f80,0x0,
0xbf353f80,0x3f358000,0x3f35bf80,0x0,0x3f350000,0x3f35bf80,0xbf358000,0x0,0x3f35bf80,0xbf358000,0xbf353f80,0x0,
0xbf350000,0xbf353f80,0x3f358000,0x0,0xbf803f80,0x80008000,0x3f80bf80,0x0,0xbf803f80,0x80008000,0x3f80bf80,0x0,
0xbf803f80,0x80008000,0x3f80bf80,0x0,0xbf803f80,0x80008000,0x3f80bf80,0x0,0xbf353f80,0xbf358000,0x3f35bf80,0x0,
0x3f350000,0xbf353f80,0xbf358000,0x0,0x3f35bf80,0x3f358000,0xbf353f80,0x0,0xbf350000,0x3f35bf80,0x3f358000,0x0,
0x3f80,0xbf808000,0x8000bf80,0x0,0xbf80,0x3f808000,0x80003f80,0x0,0x3f80,0xbf808000,0x8000bf80,0x0,
0xbf80,0x3f808000,0x80003f80,0x0,0x3f353f80,0xbf358000,0xbf35bf80,0x0,0xbf350000,0xbf35bf80,0x3f358000,0x0,
0xbf35bf80,0x3f358000,0x3f353f80,0x0,0x3f350000,0x3f353f80,0xbf358000,0x0,0x3f800000,0x0,0x3f800000,0x0,
0x3f800000,0x0,0x3f800000,0x0,0x3f800000,0x0,0x3f800000,0x0,0x3f800000,0x0,0x3f800000,0x0,
0x3f800000,0x0,0x3f7fb10f,0xbd48fb30,0x3f7ec46d,0xbdc8bd36,0x3f7d3aac,0xbe164083,0x3f7b14be,0xbe47c5c2,0x3f7853f8,0xbe78cfcc,
0x3f74fa0b,0xbe94a031,0x3f710908,0xbeac7cd4,0x3f800000,0x0,0x3f7ec46d,0xbdc8bd36,0x3f7b14be,0xbe47c5c2,0x3f74fa0b,0xbe94a031,
0x3f6c835e,0xbec3ef15,0x3f61c598,0xbef15aea,0x3f54db31,0xbf0e39da,0x3f45e403,0xbf226799,0x3f800000,0x0,0x3f7d3aac,0xbe164083,
0x3f74fa0b,0xbe94a031,0x3f676bd8,0xbedae880,0x3f54db31,0xbf0e39da,0x3f3daef9,0xbf2beb4a,0x3f226799,0xbf45e403,0x3f039c3d,0xbf5b941a,
0x3f800000,0x0,0x3f7b14be,0xbe47c5c2,0x3f6c835e,0xbec3ef15,0x3f54db31,0xbf0e39da,0x3f3504f3,0xbf3504f3,0x3f0e39da,0xbf54db31,
0x3ec3ef15,0xbf6c835e,0x3e47c5c2,0xbf7b14be,0x3f800000,0x0,0x3f7853f8,0xbe78cfcc,0x3f61c598,0xbef15aea,0x3f3daef9,0xbf2beb4a,
0x3f0e39da,0xbf54db31,0x3eac7cd4,0xbf710908,0x3dc8bd36,0xbf7ec46d,0xbe164083,0xbf7d3aac,0x3f800000,0x0,0x3f74fa0b,0xbe94a031,
0x3f54db31,0xbf0e39da,0x3f226799,0xbf45e403,0x3ec3ef15,0xbf6c835e,0x3dc8bd36,0xbf7ec46d,0xbe47c5c2,0xbf7b14be,0xbef15aea,0xbf61c598,
0x3f800000,0x0,0x3f710908,0xbeac7cd4,0x3f45e403,0xbf226799,0x3f039c3d,0xbf5b941a,0x3e47c5c2,0xbf7b14be,0xbe164083,0xbf7d3aac,
0xbef15aea,0xbf61c598,0xbf3daef9,0xbf2beb4a,0x3f800000,0x0,0x3f800000,0x0,0x3f800000,0x0,0x3f800000,0x0,
0x3f800000,0x0,0x3f800000,0x0,0x3f800000,0x0,0x3f800000,0x0,0x3f6c835e,0xbec3ef15,0x3f676bd8,0xbedae880,
0x3f61c598,0xbef15aea,0x3f5b941a,0xbf039c3d,0x3f54db31,0xbf0e39da,0x3f4d9f02,0xbf187fc0,0x3f45e403,0xbf226799,0x3f3daef9,0xbf2beb4a,
0x3f3504f3,0xbf3504f3,0x3f226799,0xbf45e403,0x3f0e39da,0xbf54db31,0x3ef15aea,0xbf61c598,0x3ec3ef15,0xbf6c835e,0x3e94a031,0xbf74fa0b,
0x3e47c5c2,0xbf7b14be,0x3dc8bd36,0xbf7ec46d,0x3ec3ef15,0xbf6c835e,0x3e78cfcc,0xbf7853f8,0x3dc8bd36,0xbf7ec46d,0xbd48fb30,0xbf7fb10f,
0xbe47c5c2,0xbf7b14be,0xbeac7cd4,0xbf710908,0xbef15aea,0xbf61c598,0xbf187fc0,0xbf4d9f02,0x0,0xbf800000,0xbe47c5c2,0xbf7b14be,
0xbec3ef15,0xbf6c835e,0xbf0e39da,0xbf54db31,0xbf3504f3,0xbf3504f3,0xbf54db31,0xbf0e39da,0xbf6c835e,0xbec3ef15,0xbf7b14be,0xbe47c5c2,
0xbec3ef15,0xbf6c835e,0xbf187fc0,0xbf4d9f02,0xbf45e403,0xbf226799,0xbf676bd8,0xbedae880,0xbf7b14be,0xbe47c5c2,0xbf7fb10f,0x3d48fb30,
0xbf74fa0b,0x3e94a031,0xbf5b941a,0x3f039c3d,0xbf3504f3,0xbf3504f3,0xbf61c598,0xbef15aea,0xbf7b14be,0xbe47c5c2,0xbf7ec46d,0x3dc8bd36,
0xbf6c835e,0x3ec3ef15,0xbf45e403,0x3f226799,0xbf0e39da,0x3f54db31,0xbe94a031,0x3f74fa0b,0xbf6c835e,0xbec3ef15,0xbf7fb10f,0xbd48fb30,
0xbf74fa0b,0x3e94a031,0xbf4d9f02,0x3f187fc0,0xbf0e39da,0x3f54db31,0xbe78cfcc,0x3f7853f8,0x3dc8bd36,0x3f7ec46d,0x3edae880,0x3f676bd8,
0x80003f80,0x3f800000,0x3f800000,0xbf80,0x3ec43f6d,0x3f6dbec4,0x3f6dbec4,0xbec4bf6d,0x3f353f35,0x3f35bf35,0x3f35bf35,0xbf35bf35,
0x3f6d3ec4,0x3ec4bf6d,0x3ec4bf6d,0xbf6dbec4,0x80003f80,0x3f800000,0xbf800000,0x3f80,0x3f6d3ec4,0x3ec4bf6d,0xbec43f6d,0x3f6d3ec4,
0x3f35bf35,0xbf35bf35,0x3f353f35,0x3f35bf35,0xbec4bf6d,0xbf6d3ec4,0x3f6dbec4,0xbec4bf6d,0x80003f80,0x3f800000,0x3f800000,0xbf80,
0x3f6dbec4,0xbec4bf6d,0xbec4bf6d,0xbf6d3ec4,0xbf35bf35,0xbf353f35,0xbf353f35,0x3f353f35,0xbec43f6d,0x3f6d3ec4,0x3f6d3ec4,0x3ec4bf6d,
0x80003f80,0x3f800000,0xbf800000,0x3f80,0x3ec4bf6d,0xbf6dbec4,0x3f6d3ec4,0x3ec4bf6d,0xbf353f35,0x3f353f35,0xbf35bf35,0xbf353f35,
0x3f6dbec4,0xbec4bf6d,0x3ec43f6d,0x3f6dbec4,0x80003f80,0x3f800000,0x3f800000,0xbf80,0xbec4bf6d,0xbf6d3ec4,0xbf6d3ec4,0x3ec43f6d,
0x3f353f35,0x3f35bf35,0x3f35bf35,0xbf35bf35,0xbf6dbec4,0xbec43f6d,0xbec43f6d,0x3f6d3ec4,0x80003f80,0x3f800000,0xbf800000,0x3f80,
0xbf6dbec4,0xbec43f6d,0x3ec4bf6d,0xbf6dbec4,0x3f35bf35,0xbf35bf35,0x3f353f35,0x3f35bf35,0x3ec43f6d,0x3f6dbec4,0xbf6d3ec4,0x3ec43f6d,
0x80003f80,0x3f800000,0x3f800000,0xbf80,0xbf6d3ec4,0x3ec43f6d,0x3ec43f6d,0x3f6dbec4,0xbf35bf35,0xbf353f35,0xbf353f35,0x3f353f35,
0x3ec4bf6d,0xbf6dbec4,0xbf6dbec4,0xbec43f6d,0x80003f80,0x3f800000,0xbf800000,0x3f80,0xbec43f6d,0x3f6d3ec4,0xbf6dbec4,0xbec43f6d,
0xbf353f35,0x3f353f35,0xbf35bf35,0xbf353f35,0xbf6d3ec4,0x3ec43f6d,0xbec4bf6d,0xbf6d3ec4,0x3f803f80,0x80008000,0xbf80bf80,0x0,
0x3f803f80,0x80008000,0xbf80bf80,0x0,0x3f803f80,0x80008000,0xbf80bf80,0x0,0x3f803f80,0x80008000,0xbf80bf80,0x0,
0x3ec43f6d,0x3f6d3ec4,0xbec4bf6d,0x0,0xbf6dbec4,0x3ec43f6d,0x3f6d3ec4,0x0,0xbec4bf6d,0xbf6dbec4,0x3ec43f6d,0x0,
0x3f6d3ec4,0xbec4bf6d,0xbf6dbec4,0x0,0xbf353f35,0x3f353f35,0x3f35bf35,0x0,0x3f35bf35,0xbf35bf35,0xbf353f35,0x0,
0xbf353f35,0x3f353f35,0x3f35bf35,0x0,0x3f35bf35,0xbf35bf35,0xbf353f35,0x0,0xbf6d3ec4,0xbec43f6d,0x3f6dbec4,0x0,
0xbec43f6d,0x3f6dbec4,0x3ec4bf6d,0x0,0x3f6dbec4,0x3ec4bf6d,0xbf6d3ec4,0x0,0x3ec4bf6d,0xbf6d3ec4,0xbec43f6d,0x0,
0x0,0xbf803f80,0x80008000,0x0,0x0,0xbf803f80,0x80008000,0x0,0x0,0xbf803f80,0x80008000,0x0,
0x0,0xbf803f80,0x80008000,0x0,0x3f6dbec4,0xbec43f6d,0xbf6d3ec4,0x0,0x3ec4bf6d,0x3f6dbec4,0xbec43f6d,0x0,
0xbf6d3ec4,0x3ec4bf6d,0x3f6dbec4,0x0,0xbec43f6d,0xbf6d3ec4,0x3ec4bf6d,0x0,0x3f35bf35,0x3f353f35,0xbf353f35,0x0,
0xbf353f35,0xbf35bf35,0x3f35bf35,0x0,0x3f35bf35,0x3f353f35,0xbf353f35,0x0,0xbf353f35,0xbf35bf35,0x3f35bf35,0x0,
0xbec4bf6d,0x3f6d3ec4,0x3ec43f6d,0x0,0x3f6d3ec4,0x3ec43f6d,0xbf6dbec4,0x0,0x3ec43f6d,0xbf6dbec4,0xbec4bf6d,0x0,
0xbf6dbec4,0xbec4bf6d,0x3f6d3ec4,0x0,0x3f800000,0x0,0x3f7fec43,0xbcc90ab0,0x3f7fb10f,0xbd48fb30,0x3f7f4e6d,0xbd96a905,
0x3f7ec46d,0xbdc8bd36,0x3f7e1324,0xbdfab273,0x3f7d3aac,0xbe164083,0x3f7c3b28,0xbe2f10a2,0x3f800000,0x0,0x3f7f4e6d,0xbd96a905,
0x3f7d3aac,0xbe164083,0x3f79c79d,0xbe605c13,0x3f74fa0b,0xbe94a031,0x3f6ed89e,0xbeb8442a,0x3f676bd8,0xbedae880,0x3f5ebe05,0xbefc5d27,
0x3f800000,0x0,0x3f7e1324,0xbdfab273,0x3f7853f8,0xbe78cfcc,0x3f6ed89e,0xbeb8442a,0x3f61c598,0xbef15aea,0x3f514d3d,0xbf13682a,
0x3f3daef9,0xbf2beb4a,0x3f273656,0xbf41d870,0x3f800000,0x0,0x3f7c3b28,0xbe2f10a2,0x3f710908,0xbeac7cd4,0x3f5ebe05,0xbefc5d27,
0x3f45e403,0xbf226799,0x3f273656,0xbf41d870,0x3f039c3d,0xbf5b941a,0x3eb8442a,0xbf6ed89e,0x3f800000,0x0,0x3f79c79d,0xbe605c13,
0x3f676bd8,0xbedae880,0x3f49d112,0xbf1d7fd1,0x3f226799,0xbf45e403,0x3ee63375,0xbf64aa59,0x3e78cfcc,0xbf7853f8,0x3cc90ab0,0xbf7fec43,
0x3f800000,0x0,0x3f76ba07,0xbe888e93,0x3f5b941a,0xbf039c3d,0x3f3085bb,0xbf396842,0x3ef15aea,0xbf61c598,0x3e605c13,0xbf79c79d,
0xbd48fb30,0xbf7fb10f,0xbea09ae5,0xbf731447,0x3f800000,0x0,0x3f731447,0xbea09ae5,0x3f4d9f02,0xbf187fc0,0x3f13682a,0xbf514d3d,
0x3e94a031,0xbf74fa0b,0xbcc90ab0,0xbf7fec43,0xbeac7cd4,0xbf710908,0xbf1d7fd1,0xbf49d112,0x3f800000,0x0,0x3f6ed89e,0xbeb8442a,
0x3f3daef9,0xbf2beb4a,0x3ee63375,0xbf64aa59,0x3dc8bd36,0xbf7ec46d,0xbe888e93,0xbf76ba07,0xbf187fc0,0xbf4d9f02,0xbf584853,0xbf08f59b,
0x3f7b14be,0xbe47c5c2,0x3f79c79d,0xbe605c13,0x3f7853f8,0xbe78cfcc,0x3f76ba07,0xbe888e93,0x3f74fa0b,0xbe94a031,0x3f731447,0xbea09ae5,
0x3f710908,0xbeac7cd4,0x3f6ed89e,0xbeb8442a,0x3f54db31,0xbf0e39da,0x3f49d112,0xbf1d7fd1,0x3f3daef9,0xbf2beb4a,0x3f3085bb,0xbf396842,
0x3f226799,0xbf45e403,0x3f13682a,0xbf514d3d,0x3f039c3d,0xbf5b941a,0x3ee63375,0xbf64aa59,0x3f0e39da,0xbf54db31,0x3ee63375,0xbf64aa59,
0x3eac7cd4,0xbf710908,0x3e605c13,0xbf79c79d,0x3dc8bd36,0xbf7ec46d,0xbcc90ab0,0xbf7fec43,0xbe164083,0xbf7d3aac,0xbe888e93,0xbf76ba07,
0x3e47c5c2,0xbf7b14be,0x3cc90ab0,0xbf7fec43,0xbe164083,0xbf7d3aac,0xbea09ae5,0xbf731447,0xbef15aea,0xbf61c598,0xbf1d7fd1,0xbf49d112,
0xbf3daef9,0xbf2beb4a,0xbf584853,0xbf08f59b,0xbe47c5c2,0xbf7b14be,0xbecf7bca,0xbf6a09a7,0xbf187fc0,0xbf4d9f02,0xbf41d870,0xbf273656,
0xbf61c598,0xbef15aea,0xbf76ba07,0xbe888e93,0xbf7fb10f,0xbd48fb30,0xbf7c3b28,0x3e2f10a2,0xbf0e39da,0xbf54db31,0xbf41d870,0xbf273656,
0xbf676bd8,0xbedae880,0xbf7c3b28,0xbe2f10a2,0xbf7ec46d,0x3dc8bd36,0xbf6ed89e,0x3eb8442a,0xbf4d9f02,0x3f187fc0,0xbf1d7fd1,0x3f49d112,
0xbf54db31,0xbf0e39da,0xbf76ba07,0xbe888e93,0xbf7fb10f,0x3d48fb30,0xbf6ed89e,0x3eb8442a,0xbf45e403,0x3f226799,0xbf08f59b,0x3f584853,
0xbe78cfcc,0x3f7853f8,0x3d96a905,0x3f7f4e6d,0xbf7b14be,0xbe47c5c2,0xbf7c3b28,0x3e2f10a2,0xbf5b941a,0x3f039c3d,0xbf1d7fd1,0x3f49d112,
0xbe94a031,0x3f74fa0b,0x3d96a905,0x3f7f4e6d,0x3edae880,0x3f676bd8,0x3f396842,0x3f3085bb,0x80003f80,0x80003f80,0x80003f80,0x80003f80,
0x80003f80,0x80003f80,0x80003f80,0x80003f80,0x80003f80,0x80003f80,0x80003f80,0x80003f80,0x80003f80,0x80003f80,0x80003f80,0x80003f80,
0x3f800000,0x3f800000,0x3f800000,0x3f800000,0x3f800000,0x3f800000,0x3f800000,0x3f800000,0x3f800000,0x3f800000,0x3f800000,0x3f800000,
0x3f800000,0x3f800000,0x3f800000,0x3f800000,0x80003f80,0x3f353f35,0x80003f80,0x3f353f35,0x3f800000,0x3f35bf35,0x3f800000,0x3f35bf35,
0x8000bf80,0xbf35bf35,0x8000bf80,0xbf35bf35,0xbf800000,0xbf353f35,0xbf800000,0xbf353f35,0x3f800000,0x3f35bf35,0x3f800000,0x3f35bf35,
0xbf80,0xbf35bf35,0xbf80,0xbf35bf35,0xbf800000,0xbf353f35,0xbf800000,0xbf353f35,0x3f80,0x3f353f35,0x3f80,0x3f353f35,
0x80003f80,0x3f800000,0x80003f80,0x3f800000,0x8000bf80,0xbf800000,0x8000bf80,0xbf800000,0x80003f80,0x3f800000,0x80003f80,0x3f800000,
0x8000bf80,0xbf800000,0x8000bf80,0xbf800000,0x3f800000,0xbf80,0x3f800000,0xbf80,0xbf800000,0x3f80,0xbf800000,0x3f80,
0x3f800000,0xbf80,0x3f800000,0xbf80,0xbf800000,0x3f80,0xbf800000,0x3f80,0x80003f80,0x3f35bf35,0x80003f80,0x3f35bf35,
0xbf800000,0x3f353f35,0xbf800000,0x3f353f35,0x8000bf80,0xbf353f35,0x8000bf80,0xbf353f35,0x3f800000,0xbf35bf35,0x3f800000,0xbf35bf35,
0x3f800000,0xbf35bf35,0x3f800000,0xbf35bf35,0x3f80,0x3f35bf35,0x3f80,0x3f35bf35,0xbf800000,0x3f353f35,0xbf800000,0x3f353f35,
0xbf80,0xbf353f35,0xbf80,0xbf353f35,0x80003f80,0x3ec43f6d,0x8000bf80,0xbec4bf6d,0x3f353f35,0x3f6d3ec4,0xbf35bf35,0xbf6dbec4,
0x3f800000,0x3f6dbec4,0xbf800000,0xbf6d3ec4,0x3f35bf35,0x3ec4bf6d,0xbf353f35,0xbec43f6d,0x3f800000,0x3f6dbec4,0xbf800000,0xbf6d3ec4,
0x3f35bf35,0x3ec4bf6d,0xbf353f35,0xbec43f6d,0xbf80,0xbec4bf6d,0x3f80,0x3ec43f6d,0xbf35bf35,0xbf6dbec4,0x3f353f35,0x3f6d3ec4,
0x80003f80,0x3f6d3ec4,0x8000bf80,0xbf6dbec4,0x3f35bf35,0xbec4bf6d,0xbf353f35,0x3ec43f6d,0xbf800000,0xbec43f6d,0x3f800000,0x3ec4bf6d,
0x3f353f35,0x3f6dbec4,0xbf35bf35,0xbf6d3ec4,0x3f800000,0x3ec4bf6d,0xbf800000,0xbec43f6d,0xbf35bf35,0xbf6d3ec4,0x3f353f35,0x3f6dbec4,
0x3f80,0x3f6d3ec4,0xbf80,0xbf6dbec4,0x3f35bf35,0xbec4bf6d,0xbf353f35,0x3ec43f6d,0x80003f80,0x3f6dbec4,0x8000bf80,0xbf6d3ec4,
0xbf35bf35,0xbec43f6d,0x3f353f35,0x3ec4bf6d,0x3f800000,0xbec4bf6d,0xbf800000,0x3ec43f6d,0xbf353f35,0x3f6d3ec4,0x3f35bf35,0xbf6dbec4,
0x3f800000,0xbec4bf6d,0xbf800000,0x3ec43f6d,0xbf353f35,0x3f6d3ec4,0x3f35bf35,0xbf6dbec4,0xbf80,0xbf6d3ec4,0x3f80,0x3f6dbec4,
0x3f353f35,0x3ec4bf6d,0xbf35bf35,0xbec43f6d,0x80003f80,0x3ec4bf6d,0x8000bf80,0xbec43f6d,0xbf353f35,0x3f6dbec4,0x3f35bf35,0xbf6d3ec4,
0xbf800000,0x3f6d3ec4,0x3f800000,0xbf6dbec4,0xbf35bf35,0x3ec43f6d,0x3f353f35,0xbec4bf6d,0x3f800000,0xbf6dbec4,0xbf800000,0x3f6d3ec4,
0x3f353f35,0xbec4bf6d,0xbf35bf35,0x3ec43f6d,0x3f80,0x3ec4bf6d,0xbf80,0xbec43f6d,0xbf353f35,0x3f6dbec4,0x3f35bf35,0xbf6d3ec4,
0x80003f80,0x8000bf80,0x80003f80,0x8000bf80,0x80003f80,0x8000bf80,0x80003f80,0x8000bf80,0x80003f80,0x8000bf80,0x80003f80,0x8000bf80,
0x80003f80,0x8000bf80,0x80003f80,0x8000bf80,0x3f800000,0xbf800000,0x3f800000,0xbf800000,0x3f800000,0xbf800000,0x3f800000,0xbf800000,
0x3f800000,0xbf800000,0x3f800000,0xbf800000,0x3f800000,0xbf800000,0x3f800000,0xbf800000,0x80003f80,0xbf35bf35,0x80003f80,0xbf35bf35,
0x3f800000,0xbf353f35,0x3f800000,0xbf353f35,0x8000bf80,0x3f353f35,0x8000bf80,0x3f353f35,0xbf800000,0x3f35bf35,0xbf800000,0x3f35bf35,
0x3f800000,0xbf353f35,0x3f800000,0xbf353f35,0xbf80,0x3f353f35,0xbf80,0x3f353f35,0xbf800000,0x3f35bf35,0xbf800000,0x3f35bf35,
0x3f80,0xbf35bf35,0x3f80,0xbf35bf35,0x80003f80,0xbf800000,0x80003f80,0xbf800000,0x8000bf80,0x3f800000,0x8000bf80,0x3f800000,
0x80003f80,0xbf800000,0x80003f80,0xbf800000,0x8000bf80,0x3f800000,0x8000bf80,0x3f800000,0x3f800000,0x3f80,0x3f800000,0x3f80,
0xbf800000,0xbf80,0xbf800000,0xbf80,0x3f800000,0x3f80,0x3f800000,0x3f80,0xbf800000,0xbf80,0xbf800000,0xbf80,
0x80003f80,0xbf353f35,0x80003f80,0xbf353f35,0xbf800000,0xbf35bf35,0xbf800000,0xbf35bf35,0x8000bf80,0x3f35bf35,0x8000bf80,0x3f35bf35,
0x3f800000,0x3f353f35,0x3f800000,0x3f353f35,0x3f800000,0x3f353f35,0x3f800000,0x3f353f35,0x3f80,0xbf353f35,0x3f80,0xbf353f35,
0xbf800000,0xbf35bf35,0xbf800000,0xbf35bf35,0xbf80,0x3f35bf35,0xbf80,0x3f35bf35,0x80003f80,0xbec4bf6d,0x8000bf80,0x3ec43f6d,
0x3f353f35,0xbf6dbec4,0xbf35bf35,0x3f6d3ec4,0x3f800000,0xbf6d3ec4,0xbf800000,0x3f6dbec4,0x3f35bf35,0xbec43f6d,0xbf353f35,0x3ec4bf6d,
0x3f800000,0xbf6d3ec4,0xbf800000,0x3f6dbec4,0x3f35bf35,0xbec43f6d,0xbf353f35,0x3ec4bf6d,0xbf80,0x3ec43f6d,0x3f80,0xbec4bf6d,
0xbf35bf35,0x3f6d3ec4,0x3f353f35,0xbf6dbec4,0x80003f80,0xbf6dbec4,0x8000bf80,0x3f6d3ec4,0x3f35bf35,0x3ec43f6d,0xbf353f35,0xbec4bf6d,
0xbf800000,0x3ec4bf6d,0x3f800000,0xbec43f6d,0x3f353f35,0xbf6d3ec4,0xbf35bf35,0x3f6dbec4,0x3f800000,0xbec43f6d,0xbf800000,0x3ec4bf6d,
0xbf35bf35,0x3f6dbec4,0x3f353f35,0xbf6d3ec4,0x3f80,0xbf6dbec4,0xbf80,0x3f6d3ec4,0x3f35bf35,0x3ec43f6d,0xbf353f35,0xbec4bf6d,
0x80003f80,0xbf6d3ec4,0x8000bf80,0x3f6dbec4,0xbf35bf35,0x3ec4bf6d,0x3f353f35,0xbec43f6d,0x3f800000,0x3ec43f6d,0xbf800000,0xbec4bf6d,
0xbf353f35,0xbf6dbec4,0x3f35bf35,0x3f6d3ec4,0x3f800000,0x3ec43f6d,0xbf800000,0xbec4bf6d,0xbf353f35,0xbf6dbec4,0x3f35bf35,0x3f6d3ec4,
0xbf80,0x3f6dbec4,0x3f80,0xbf6d3ec4,0x3f353f35,0xbec43f6d,0xbf35bf35,0x3ec4bf6d,0x80003f80,0xbec43f6d,0x8000bf80,0x3ec4bf6d,
0xbf353f35,0xbf6d3ec4,0x3f35bf35,0x3f6dbec4,0xbf800000,0xbf6dbec4,0x3f800000,0x3f6d3ec4,0xbf35bf35,0xbec4bf6d,0x3f353f35,0x3ec43f6d,
0x3f800000,0x3f6d3ec4,0xbf800000,0xbf6dbec4,0x3f353f35,0x3ec43f6d,0xbf35bf35,0xbec4bf6d,0x3f80,0xbec43f6d,0xbf80,0x3ec4bf6d,
0xbf353f35,0xbf6d3ec4,0x3f35bf35,0x3f6dbec4,
};
constexpr int TB_F = 0, TB_E = 512, TB_P2 = 1024;

enum { C_EP = 0, C_Z1 = 32, C_Z2 = 96, C_H3 = 128, C_U = 160, C_TOTAL = 256 };
struct Scratch {
  unsigned cnt[C_TOTAL];
  uint32_t mod[6 * D_ + 384];
  uint32_t z1[120 * 5120];
  uint32_t z2[128 * 4800];
  uint32_t x1[S_ * D_ / 2];
  uint8_t h3[32 * 18 * 4096];
  uint8_t u[72 * D_ * 128];
};
__device__ __align__(1024) Scratch g_s;

#define PF2 8
#define PF2K 16
#define HOLDA 3
#define GOAT 1
#define HOLD1 0
#define NG1 4

#define CK(k) do {} while (0)
#define TS(k) do {} while (0)
#define TSC(k) do {} while (0)
struct Maps { CUtensorMap w1a, w1b, w2, x1, out, z1, z2, h3; };
struct Params {
  const __nv_bfloat16 *x, *c, *wmod;
  Scratch* s;
  const uint4* tab;
  const __nv_bfloat16 *wr, *wi, *w1, *w2, *b1, *b2;
};

__device__ __forceinline__ uint32_t smem_u32(const void* p) { return (uint32_t)__cvta_generic_to_shared(p); }
__device__ __forceinline__ void mbar_init(uint32_t b, int c) { asm volatile("mbarrier.init.shared::cta.b64 [%0], %1;" ::"r"(b), "r"(c)); }
__device__ __forceinline__ void mbar_expect(uint32_t b, int bytes) { asm volatile("mbarrier.arrive.expect_tx.shared::cta.b64 _, [%0], %1;" ::"r"(b), "r"(bytes) : "memory"); }
__device__ __forceinline__ void mbar_arrive(uint32_t b) { asm volatile("mbarrier.arrive.shared::cta.b64 _, [%0];" ::"r"(b) : "memory"); }
__device__ __forceinline__ bool mbar_try(uint32_t b, int ph) {
  uint32_t ok;
  asm volatile("{\n.reg .pred p;\nmbarrier.try_wait.parity.shared::cta.b64 p, [%1], %2;\nselp.u32 %0, 1, 0, p;\n}\n" : "=r"(ok) : "r"(b), "r"(ph) : "memory");
  return ok;
}
__device__ __forceinline__ void mbar_wait(uint32_t b, int ph) {
  if (__builtin_expect(!mbar_try(b, ph), 0)) {
    int it = 0;
    while (!mbar_try(b, ph)) if (++it > (1 << 22)) __trap();
  }
}
__device__ __forceinline__ void mbar_spin(uint32_t b, int ph) {
  int it = 0;
  while (!mbar_try(b, ph)) if (++it > (1 << 22)) __trap();
}
__device__ __forceinline__ void mbar_wait_cluster(uint32_t b, int ph) {
  uint32_t ok; int it = 0;
  do {
    asm volatile("{\n.reg .pred p;\nmbarrier.try_wait.parity.acquire.cluster.shared::cta.b64 p, [%1], %2;\nselp.u32 %0, 1, 0, p;\n}\n" : "=r"(ok) : "r"(b), "r"(ph) : "memory");
    if (!ok && ++it > (1 << 22)) __trap();
  } while (!ok);
}
__device__ __forceinline__ void tma2d(uint32_t dst, const CUtensorMap* m, int c0, int c1, uint32_t bar) {
  asm volatile("cp.async.bulk.tensor.2d.shared::cluster.global.mbarrier::complete_tx::bytes [%0], [%1, {%3, %4}], [%2];" ::"r"(dst), "l"(m), "r"(bar), "r"(c0), "r"(c1) : "memory");
}
__device__ __forceinline__ uint64_t pol_ef() { uint64_t p; asm("createpolicy.fractional.L2::evict_first.b64 %0, 1.0;" : "=l"(p)); return p; }
__device__ __forceinline__ void tma3d_ef(uint32_t dst, const CUtensorMap* m, int c1, int c2, uint32_t bar) {
  asm volatile("cp.async.bulk.tensor.3d.shared::cluster.global.mbarrier::complete_tx::bytes.L2::cache_hint [%0], [%1, {%3, %4, %5}], [%2], %6;" ::"r"(dst), "l"(m), "r"(bar), "r"(0), "r"(c1), "r"(c2), "l"(pol_ef()) : "memory");
}
__device__ __forceinline__ void tma4d_ef(uint32_t dst, const CUtensorMap* m, int c2, int c3, uint32_t bar) {
  asm volatile("cp.async.bulk.tensor.4d.shared::cluster.global.mbarrier::complete_tx::bytes.L2::cache_hint [%0], [%1, {%3, %3, %4, %5}], [%2], %6;" ::"r"(dst), "l"(m), "r"(bar), "r"(0), "r"(c2), "r"(c3), "l"(pol_ef()) : "memory");
}
__device__ __forceinline__ void bulk_ld(uint32_t dst, const void* src, int bytes, uint32_t bar) {
  asm volatile("cp.async.bulk.shared::cluster.global.mbarrier::complete_tx::bytes [%0], [%1], %2, [%3];" ::"r"(dst), "l"(src), "r"(bytes), "r"(bar) : "memory");
}
__device__ __forceinline__ void bulk_st(void* dst, uint32_t src, int bytes) {
  asm volatile("cp.async.bulk.global.shared::cta.bulk_group [%0], [%1], %2;" ::"l"(dst), "r"(src), "r"(bytes) : "memory");
}
__device__ __forceinline__ void tma_st2d(const CUtensorMap* m, uint32_t src, int c0, int c1) {
  asm volatile("cp.async.bulk.tensor.2d.global.shared::cta.bulk_group [%0, {%2, %3}], [%1];" ::"l"(m), "r"(src), "r"(c0), "r"(c1) : "memory");
}
__device__ __forceinline__ void bulk_commit_wait_read() {
  asm volatile("cp.async.bulk.commit_group;" ::: "memory");
  asm volatile("cp.async.bulk.wait_group.read 0;" ::: "memory");
}
__device__ __forceinline__ void bulk_commit_wait() {
  asm volatile("cp.async.bulk.commit_group;" ::: "memory");
  asm volatile("cp.async.bulk.wait_group 0;" ::: "memory");
}
__device__ __forceinline__ void prefetch_l2(const void* p, int bytes) {
  asm volatile("cp.async.bulk.prefetch.L2.global [%0], %1;" ::"l"(p), "r"(bytes) : "memory");
}
__device__ __forceinline__ void wg_fence() { asm volatile("wgmma.fence.sync.aligned;" ::: "memory"); }
__device__ __forceinline__ void wg_commit() { asm volatile("wgmma.commit_group.sync.aligned;" ::: "memory"); }
template <int N> __device__ __forceinline__ void wg_wait() { asm volatile("wgmma.wait_group.sync.aligned %0;" ::"n"(N) : "memory"); }
template <int N> __device__ __forceinline__ void reg_fence(float (&d)[N]) {
#pragma unroll
  for (int i = 0; i < N; i++) asm volatile("" : "+f"(d[i])::"memory");
}
__device__ __forceinline__ void fence_async_smem() { asm volatile("fence.proxy.async.shared::cta;" ::: "memory"); }
__device__ __forceinline__ void fence_async_glb() { asm volatile("fence.proxy.async.global;" ::: "memory"); }
__device__ __forceinline__ uint32_t ld_rlx(const void* p) { uint32_t v; asm volatile("ld.relaxed.gpu.global.b32 %0, [%1];" : "=r"(v) : "l"(p) : "memory"); return v; }
__device__ __forceinline__ uint2 ld_rlx2(const void* p) { uint2 v; asm volatile("ld.relaxed.gpu.global.v2.b32 {%0,%1}, [%2];" : "=r"(v.x), "=r"(v.y) : "l"(p) : "memory"); return v; }
__device__ __forceinline__ uint4 ld_rlx4(const void* p) { uint4 v; asm volatile("ld.relaxed.gpu.global.v4.b32 {%0,%1,%2,%3}, [%4];" : "=r"(v.x), "=r"(v.y), "=r"(v.z), "=r"(v.w) : "l"(p) : "memory"); return v; }
__device__ __forceinline__ uint32_t lds(uint32_t a) { uint32_t v; asm volatile("ld.shared.b32 %0, [%1];" : "=r"(v) : "r"(a) : "memory"); return v; }
__device__ __forceinline__ uint2 lds2(uint32_t a) { uint2 v; asm volatile("ld.shared.v2.b32 {%0,%1}, [%2];" : "=r"(v.x), "=r"(v.y) : "r"(a) : "memory"); return v; }
__device__ __forceinline__ uint4 lds4(uint32_t a) { uint4 v; asm volatile("ld.shared.v4.b32 {%0,%1,%2,%3}, [%4];" : "=r"(v.x), "=r"(v.y), "=r"(v.z), "=r"(v.w) : "r"(a) : "memory"); return v; }
__device__ __forceinline__ float lds_bf(uint32_t a) { uint32_t v; asm volatile("ld.shared.u16 %0, [%1];" : "=r"(v) : "r"(a) : "memory"); return __uint_as_float(v << 16); }
__device__ __forceinline__ void sts(uint32_t a, uint32_t v) { asm volatile("st.shared.b32 [%0], %1;" ::"r"(a), "r"(v) : "memory"); }
__device__ __forceinline__ void sts2(uint32_t a, uint32_t v0, uint32_t v1) { asm volatile("st.shared.v2.b32 [%0], {%1,%2};" ::"r"(a), "r"(v0), "r"(v1) : "memory"); }
__device__ __forceinline__ void sts4(uint32_t a, uint32_t v0, uint32_t v1, uint32_t v2, uint32_t v3) { asm volatile("st.shared.v4.b32 [%0], {%1,%2,%3,%4};" ::"r"(a), "r"(v0), "r"(v1), "r"(v2), "r"(v3) : "memory"); }
__device__ __forceinline__ void bar_sync(int id, int n) { asm volatile("bar.sync %0, %1;" ::"r"(id), "r"(n) : "memory"); }
__device__ __forceinline__ void bar_arrive(int id, int n) { asm volatile("bar.arrive %0, %1;" ::"r"(id), "r"(n) : "memory"); }
__device__ __forceinline__ void red_add(unsigned* p, unsigned v) { asm volatile("red.relaxed.gpu.global.add.u32 [%0], %1;" ::"l"(p), "r"(v) : "memory"); }
__device__ __forceinline__ void wait_cnt(const unsigned* p, unsigned target) {
  int it = 0;
  while ((int)(ld_rlx(p) - target) < 0) if (++it > (1 << 21)) __trap();
}
__device__ __forceinline__ uint32_t pack_bf16(float lo, float hi) { uint32_t r; asm("cvt.rn.bf16x2.f32 %0, %1, %2;" : "=r"(r) : "f"(hi), "f"(lo)); return r; }
__device__ __forceinline__ float bf_lo(uint32_t v) { return __uint_as_float(v << 16); }
__device__ __forceinline__ float bf_hi(uint32_t v) { return __uint_as_float(v & 0xffff0000u); }
__device__ __forceinline__ uint32_t hadd2(uint32_t a, uint32_t b) { uint32_t r; asm("add.rn.bf16x2 %0, %1, %2;" : "=r"(r) : "r"(a), "r"(b)); return r; }
__device__ __forceinline__ uint32_t hmul2(uint32_t a, uint32_t b) { uint32_t r; asm("mul.rn.bf16x2 %0, %1, %2;" : "=r"(r) : "r"(a), "r"(b)); return r; }
__device__ __forceinline__ uint32_t hfma2(uint32_t a, uint32_t b, uint32_t c) { uint32_t r; asm("fma.rn.bf16x2 %0, %1, %2, %3;" : "=r"(r) : "r"(a), "r"(b), "r"(c)); return r; }
__device__ __forceinline__ float rbf(float x) { uint32_t r; asm("cvt.rn.bf16x2.f32 %0, %1, %2;" : "=r"(r) : "f"(x), "f"(0.0f)); return __uint_as_float(r); }
__device__ __forceinline__ void stmatrix4(uint32_t a, uint32_t r0, uint32_t r1, uint32_t r2, uint32_t r3) {
  asm volatile("stmatrix.sync.aligned.m8n8.x4.shared.b16 [%0], {%1,%2,%3,%4};" ::"r"(a), "r"(r0), "r"(r1), "r"(r2), "r"(r3) : "memory");
}
__device__ __forceinline__ void stmatrix2(uint32_t a, uint32_t r0, uint32_t r1) {
  asm volatile("stmatrix.sync.aligned.m8n8.x2.shared.b16 [%0], {%1,%2};" ::"r"(a), "r"(r0), "r"(r1) : "memory");
}
__device__ __forceinline__ void stmatrix4t(uint32_t a, uint32_t r0, uint32_t r1, uint32_t r2, uint32_t r3) {
  asm volatile("stmatrix.sync.aligned.m8n8.x4.trans.shared.b16 [%0], {%1,%2,%3,%4};" ::"r"(a), "r"(r0), "r"(r1), "r"(r2), "r"(r3) : "memory");
}
__device__ __forceinline__ uint32_t movm(uint32_t a) { uint32_t r; asm("movmatrix.sync.aligned.m8n8.trans.b16 %0, %1;" : "=r"(r) : "r"(a)); return r; }
template <bool ACC> __device__ __forceinline__ void mma16(float* d, uint32_t a0, uint32_t a1, uint32_t a2, uint32_t a3, uint32_t b0, uint32_t b1) {
  if (ACC) asm("mma.sync.aligned.m16n8k16.row.col.f32.bf16.bf16.f32 {%0,%1,%2,%3}, {%4,%5,%6,%7}, {%8,%9}, {%0,%1,%2,%3};"
               : "+f"(d[0]), "+f"(d[1]), "+f"(d[2]), "+f"(d[3]) : "r"(a0), "r"(a1), "r"(a2), "r"(a3), "r"(b0), "r"(b1));
  else asm("mma.sync.aligned.m16n8k16.row.col.f32.bf16.bf16.f32 {%0,%1,%2,%3}, {%4,%5,%6,%7}, {%8,%9}, {%10,%10,%10,%10};"
           : "=f"(d[0]), "=f"(d[1]), "=f"(d[2]), "=f"(d[3]) : "r"(a0), "r"(a1), "r"(a2), "r"(a3), "r"(b0), "r"(b1), "f"(0.f));
}
__device__ __forceinline__ float2 cmul(float2 a, float2 b) { return make_float2(a.x * b.x - a.y * b.y, a.x * b.y + a.y * b.x); }

template<int TB> __device__ __forceinline__ void wgmma_ss_160_0(float (&d)[80], uint32_t al, uint32_t ah, uint32_t bl, uint32_t bh) {
  asm volatile("{\n.reg .b64 da, db;\nmov.b64 da, {%80, %81};\nmov.b64 db, {%82, %83};\n"
    "wgmma.mma_async.sync.aligned.m64n160k16.f32.bf16.bf16 {%0,%1,%2,%3,%4,%5,%6,%7,%8,%9,%10,%11,%12,%13,%14,%15,%16,%17,%18,%19,%20,%21,%22,%23,%24,%25,%26,%27,%28,%29,%30,%31,%32,%33,%34,%35,%36,%37,%38,%39,%40,%41,%42,%43,%44,%45,%46,%47,%48,%49,%50,%51,%52,%53,%54,%55,%56,%57,%58,%59,%60,%61,%62,%63,%64,%65,%66,%67,%68,%69,%70,%71,%72,%73,%74,%75,%76,%77,%78,%79}, da, db, 1, 1, 1, 1, %84;\n}\n"
    : "+f"(d[0]),"+f"(d[1]),"+f"(d[2]),"+f"(d[3]),"+f"(d[4]),"+f"(d[5]),"+f"(d[6]),"+f"(d[7]),"+f"(d[8]),"+f"(d[9]),"+f"(d[10]),"+f"(d[11]),"+f"(d[12]),"+f"(d[13]),"+f"(d[14]),"+f"(d[15]),"+f"(d[16]),"+f"(d[17]),"+f"(d[18]),"+f"(d[19]),"+f"(d[20]),"+f"(d[21]),"+f"(d[22]),"+f"(d[23]),"+f"(d[24]),"+f"(d[25]),"+f"(d[26]),"+f"(d[27]),"+f"(d[28]),"+f"(d[29]),"+f"(d[30]),"+f"(d[31]),"+f"(d[32]),"+f"(d[33]),"+f"(d[34]),"+f"(d[35]),"+f"(d[36]),"+f"(d[37]),"+f"(d[38]),"+f"(d[39]),"+f"(d[40]),"+f"(d[41]),"+f"(d[42]),"+f"(d[43]),"+f"(d[44]),"+f"(d[45]),"+f"(d[46]),"+f"(d[47]),"+f"(d[48]),"+f"(d[49]),"+f"(d[50]),"+f"(d[51]),"+f"(d[52]),"+f"(d[53]),"+f"(d[54]),"+f"(d[55]),"+f"(d[56]),"+f"(d[57]),"+f"(d[58]),"+f"(d[59]),"+f"(d[60]),"+f"(d[61]),"+f"(d[62]),"+f"(d[63]),"+f"(d[64]),"+f"(d[65]),"+f"(d[66]),"+f"(d[67]),"+f"(d[68]),"+f"(d[69]),"+f"(d[70]),"+f"(d[71]),"+f"(d[72]),"+f"(d[73]),"+f"(d[74]),"+f"(d[75]),"+f"(d[76]),"+f"(d[77]),"+f"(d[78]),"+f"(d[79])
    : "r"(al), "r"(ah), "r"(bl), "r"(bh), "n"(TB));
}
template<int TB> __device__ __forceinline__ void wgmma_ss_144_0(float (&d)[80], uint32_t al, uint32_t ah, uint32_t bl, uint32_t bh) {
  asm volatile("{\n.reg .b64 da, db;\nmov.b64 da, {%72, %73};\nmov.b64 db, {%74, %75};\n"
    "wgmma.mma_async.sync.aligned.m64n144k16.f32.bf16.bf16 {%0,%1,%2,%3,%4,%5,%6,%7,%8,%9,%10,%11,%12,%13,%14,%15,%16,%17,%18,%19,%20,%21,%22,%23,%24,%25,%26,%27,%28,%29,%30,%31,%32,%33,%34,%35,%36,%37,%38,%39,%40,%41,%42,%43,%44,%45,%46,%47,%48,%49,%50,%51,%52,%53,%54,%55,%56,%57,%58,%59,%60,%61,%62,%63,%64,%65,%66,%67,%68,%69,%70,%71}, da, db, 1, 1, 1, 1, %76;\n}\n"
    : "+f"(d[0]),"+f"(d[1]),"+f"(d[2]),"+f"(d[3]),"+f"(d[4]),"+f"(d[5]),"+f"(d[6]),"+f"(d[7]),"+f"(d[8]),"+f"(d[9]),"+f"(d[10]),"+f"(d[11]),"+f"(d[12]),"+f"(d[13]),"+f"(d[14]),"+f"(d[15]),"+f"(d[16]),"+f"(d[17]),"+f"(d[18]),"+f"(d[19]),"+f"(d[20]),"+f"(d[21]),"+f"(d[22]),"+f"(d[23]),"+f"(d[24]),"+f"(d[25]),"+f"(d[26]),"+f"(d[27]),"+f"(d[28]),"+f"(d[29]),"+f"(d[30]),"+f"(d[31]),"+f"(d[32]),"+f"(d[33]),"+f"(d[34]),"+f"(d[35]),"+f"(d[36]),"+f"(d[37]),"+f"(d[38]),"+f"(d[39]),"+f"(d[40]),"+f"(d[41]),"+f"(d[42]),"+f"(d[43]),"+f"(d[44]),"+f"(d[45]),"+f"(d[46]),"+f"(d[47]),"+f"(d[48]),"+f"(d[49]),"+f"(d[50]),"+f"(d[51]),"+f"(d[52]),"+f"(d[53]),"+f"(d[54]),"+f"(d[55]),"+f"(d[56]),"+f"(d[57]),"+f"(d[58]),"+f"(d[59]),"+f"(d[60]),"+f"(d[61]),"+f"(d[62]),"+f"(d[63]),"+f"(d[64]),"+f"(d[65]),"+f"(d[66]),"+f"(d[67]),"+f"(d[68]),"+f"(d[69]),"+f"(d[70]),"+f"(d[71])
    : "r"(al), "r"(ah), "r"(bl), "r"(bh), "n"(TB));
}
template<int TB> __device__ __forceinline__ void wgmma_ss_96_0(float (&d)[80], uint32_t al, uint32_t ah, uint32_t bl, uint32_t bh) {
  asm volatile("{\n.reg .b64 da, db;\nmov.b64 da, {%48, %49};\nmov.b64 db, {%50, %51};\n"
    "wgmma.mma_async.sync.aligned.m64n96k16.f32.bf16.bf16 {%0,%1,%2,%3,%4,%5,%6,%7,%8,%9,%10,%11,%12,%13,%14,%15,%16,%17,%18,%19,%20,%21,%22,%23,%24,%25,%26,%27,%28,%29,%30,%31,%32,%33,%34,%35,%36,%37,%38,%39,%40,%41,%42,%43,%44,%45,%46,%47}, da, db, 1, 1, 1, 1, %52;\n}\n"
    : "+f"(d[0]),"+f"(d[1]),"+f"(d[2]),"+f"(d[3]),"+f"(d[4]),"+f"(d[5]),"+f"(d[6]),"+f"(d[7]),"+f"(d[8]),"+f"(d[9]),"+f"(d[10]),"+f"(d[11]),"+f"(d[12]),"+f"(d[13]),"+f"(d[14]),"+f"(d[15]),"+f"(d[16]),"+f"(d[17]),"+f"(d[18]),"+f"(d[19]),"+f"(d[20]),"+f"(d[21]),"+f"(d[22]),"+f"(d[23]),"+f"(d[24]),"+f"(d[25]),"+f"(d[26]),"+f"(d[27]),"+f"(d[28]),"+f"(d[29]),"+f"(d[30]),"+f"(d[31]),"+f"(d[32]),"+f"(d[33]),"+f"(d[34]),"+f"(d[35]),"+f"(d[36]),"+f"(d[37]),"+f"(d[38]),"+f"(d[39]),"+f"(d[40]),"+f"(d[41]),"+f"(d[42]),"+f"(d[43]),"+f"(d[44]),"+f"(d[45]),"+f"(d[46]),"+f"(d[47])
    : "r"(al), "r"(ah), "r"(bl), "r"(bh), "n"(TB));
}
template<int TB> __device__ __forceinline__ void wgmma_ss_48_48(float (&d)[80], uint32_t al, uint32_t ah, uint32_t bl, uint32_t bh) {
  asm volatile("{\n.reg .b64 da, db;\nmov.b64 da, {%24, %25};\nmov.b64 db, {%26, %27};\n"
    "wgmma.mma_async.sync.aligned.m64n48k16.f32.bf16.bf16 {%0,%1,%2,%3,%4,%5,%6,%7,%8,%9,%10,%11,%12,%13,%14,%15,%16,%17,%18,%19,%20,%21,%22,%23}, da, db, 1, 1, 1, 1, %28;\n}\n"
    : "+f"(d[48]),"+f"(d[49]),"+f"(d[50]),"+f"(d[51]),"+f"(d[52]),"+f"(d[53]),"+f"(d[54]),"+f"(d[55]),"+f"(d[56]),"+f"(d[57]),"+f"(d[58]),"+f"(d[59]),"+f"(d[60]),"+f"(d[61]),"+f"(d[62]),"+f"(d[63]),"+f"(d[64]),"+f"(d[65]),"+f"(d[66]),"+f"(d[67]),"+f"(d[68]),"+f"(d[69]),"+f"(d[70]),"+f"(d[71])
    : "r"(al), "r"(ah), "r"(bl), "r"(bh), "n"(TB));
}
__device__ __forceinline__ void wgmma_rs_72(float (&d)[36], uint32_t a0, uint32_t a1, uint32_t a2, uint32_t a3, uint32_t bl, uint32_t bh, int sd) {
  asm volatile("{\n.reg .pred p;\n.reg .b64 db;\nsetp.ne.b32 p, %42, 0;\nmov.b64 db, {%40, %41};\n"
    "wgmma.mma_async.sync.aligned.m64n72k16.f32.bf16.bf16 {%0,%1,%2,%3,%4,%5,%6,%7,%8,%9,%10,%11,%12,%13,%14,%15,%16,%17,%18,%19,%20,%21,%22,%23,%24,%25,%26,%27,%28,%29,%30,%31,%32,%33,%34,%35}, {%36,%37,%38,%39}, db, p, 1, 1, 1;\n}\n"
    : "+f"(d[0]),"+f"(d[1]),"+f"(d[2]),"+f"(d[3]),"+f"(d[4]),"+f"(d[5]),"+f"(d[6]),"+f"(d[7]),"+f"(d[8]),"+f"(d[9]),"+f"(d[10]),"+f"(d[11]),"+f"(d[12]),"+f"(d[13]),"+f"(d[14]),"+f"(d[15]),"+f"(d[16]),"+f"(d[17]),"+f"(d[18]),"+f"(d[19]),"+f"(d[20]),"+f"(d[21]),"+f"(d[22]),"+f"(d[23]),"+f"(d[24]),"+f"(d[25]),"+f"(d[26]),"+f"(d[27]),"+f"(d[28]),"+f"(d[29]),"+f"(d[30]),"+f"(d[31]),"+f"(d[32]),"+f"(d[33]),"+f"(d[34]),"+f"(d[35])
    : "r"(a0), "r"(a1), "r"(a2), "r"(a3), "r"(bl), "r"(bh), "r"(sd));
}
__device__ __forceinline__ void wgmma_rs_48(float (&d)[24], uint32_t a0, uint32_t a1, uint32_t a2, uint32_t a3, uint32_t bl, uint32_t bh, int sd) {
  asm volatile("{\n.reg .pred p;\n.reg .b64 db;\nsetp.ne.b32 p, %30, 0;\nmov.b64 db, {%28, %29};\n"
    "wgmma.mma_async.sync.aligned.m64n48k16.f32.bf16.bf16 {%0,%1,%2,%3,%4,%5,%6,%7,%8,%9,%10,%11,%12,%13,%14,%15,%16,%17,%18,%19,%20,%21,%22,%23}, {%24,%25,%26,%27}, db, p, 1, 1, 1;\n}\n"
    : "+f"(d[0]),"+f"(d[1]),"+f"(d[2]),"+f"(d[3]),"+f"(d[4]),"+f"(d[5]),"+f"(d[6]),"+f"(d[7]),"+f"(d[8]),"+f"(d[9]),"+f"(d[10]),"+f"(d[11]),"+f"(d[12]),"+f"(d[13]),"+f"(d[14]),"+f"(d[15]),"+f"(d[16]),"+f"(d[17]),"+f"(d[18]),"+f"(d[19]),"+f"(d[20]),"+f"(d[21]),"+f"(d[22]),"+f"(d[23])
    : "r"(a0), "r"(a1), "r"(a2), "r"(a3), "r"(bl), "r"(bh), "r"(sd));
}
template<int N,int OFF,int TB> __device__ __forceinline__ void wgmma_ss(float (&d)[80], uint32_t al, uint32_t ah, uint32_t bl, uint32_t bh) {
  if constexpr (N==160) wgmma_ss_160_0<TB>(d, al, ah, bl, bh);
  else if constexpr (N==144) wgmma_ss_144_0<TB>(d, al, ah, bl, bh);
  else if constexpr (N==96) wgmma_ss_96_0<TB>(d, al, ah, bl, bh);
  else if constexpr (N==48) wgmma_ss_48_48<TB>(d, al, ah, bl, bh);
}

__device__ __forceinline__ void dft3(float2& a, float2& b, float2& c) {
  const float s = 0.86602540378443864676f;
  float2 t = make_float2(b.x + c.x, b.y + c.y), d = make_float2(b.x - c.x, b.y - c.y);
  float2 m = make_float2(fmaf(-0.5f, t.x, a.x), fmaf(-0.5f, t.y, a.y));
  a = make_float2(a.x + t.x, a.y + t.y);
  b = make_float2(fmaf(s, d.y, m.x), fmaf(-s, d.x, m.y));
  c = make_float2(fmaf(-s, d.y, m.x), fmaf(s, d.x, m.y));
}
__device__ __forceinline__ void dft9(float2 (&x)[9]) {
  const float2 w1 = make_float2(0.76604444311897803520f, -0.64278760968653932632f);
  const float2 w2 = make_float2(0.17364817766693034885f, -0.98480775301220805937f);
  const float2 w4 = make_float2(-0.93969262078590838405f, -0.34202014332566873304f);
  dft3(x[0], x[3], x[6]); dft3(x[1], x[4], x[7]); dft3(x[2], x[5], x[8]);
  x[4] = cmul(x[4], w1); x[7] = cmul(x[7], w2); x[5] = cmul(x[5], w2); x[8] = cmul(x[8], w4);
  dft3(x[0], x[1], x[2]); dft3(x[3], x[4], x[5]); dft3(x[6], x[7], x[8]);
  float2 t;
  t = x[1]; x[1] = x[3]; x[3] = t;
  t = x[2]; x[2] = x[6]; x[6] = t;
  t = x[5]; x[5] = x[7]; x[7] = t;
}

template <int NU>
__device__ __forceinline__ void mod_unit(const Params& p, int u, int t128, const float (&sil)[9], uint32_t red, uint32_t tag) {
  const uint4* src = reinterpret_cast<const uint4*>(p.wmod + (size_t)(t128 >> 1) * (6 * D_) + 16 * u) + (t128 & 1);
  float acc[8];
#pragma unroll
  for (int e = 0; e < 8; e++) acc[e] = 0.f;
#pragma unroll
  for (int i0 = 0; i0 < 9; i0 += NU) {
    uint4 wv[NU];
#pragma unroll
    for (int i = 0; i < NU; i++) wv[i] = __ldg(src + (size_t)(i0 + i) * (64 * 6 * D_ / 8));
#pragma unroll
    for (int i = 0; i < NU; i++) {
      const float sc = sil[i0 + i];
      acc[0] = fmaf(sc, bf_lo(wv[i].x), acc[0]); acc[1] = fmaf(sc, bf_hi(wv[i].x), acc[1]);
      acc[2] = fmaf(sc, bf_lo(wv[i].y), acc[2]); acc[3] = fmaf(sc, bf_hi(wv[i].y), acc[3]);
      acc[4] = fmaf(sc, bf_lo(wv[i].z), acc[4]); acc[5] = fmaf(sc, bf_hi(wv[i].z), acc[5]);
      acc[6] = fmaf(sc, bf_lo(wv[i].w), acc[6]); acc[7] = fmaf(sc, bf_hi(wv[i].w), acc[7]);
    }
  }
#pragma unroll
  for (int n = 4, o = 2; n; n >>= 1, o <<= 1) {
    const bool up = t128 & o;
#pragma unroll
    for (int e = 0; e < n; e++) acc[e] = (up ? acc[e + n] : acc[e]) + __shfl_xor_sync(0xffffffffu, up ? acc[e] : acc[e + n], o);
  }
  acc[0] += __shfl_xor_sync(0xffffffffu, acc[0], 16);
  const int col = 8 * (t128 & 1) + 2 * (t128 & 2) + ((t128 >> 1) & 2) + ((t128 >> 3) & 1);
  if (!(t128 & 16)) sts(red + (col * 4 + (t128 >> 5)) * 4, __float_as_uint(acc[0]));
  bar_sync(4, 128);
  if (t128 < 16) {
    const uint4 v = lds4(red + t128 * 16);
    float m = rbf((__uint_as_float(v.x) + __uint_as_float(v.y)) + (__uint_as_float(v.z) + __uint_as_float(v.w)));
    const int kind = u / 36;
    if (kind == 0) m *= 16.0f;
    if (kind == 1 || kind == 4) m = rbf(1.0f + m);
    p.s->mod[16 * u + (kind < 2 ? 2 * (t128 & 7) + (t128 >> 3) : t128)] = __float_as_uint(m) | tag;
  }
}

__device__ __forceinline__ void ln_stats2(const float (&a)[18], const float (&b)[18], float sc, float& oa, float& ra, float& ob, float& rb) {
  float v[4] = {0.f, 0.f, 0.f, 0.f}, w[4] = {0.f, 0.f, 0.f, 0.f};
#pragma unroll
  for (int i = 0; i < 18; i += 2) {
    v[0] += a[i]; v[1] = fmaf(a[i], a[i], v[1]); v[2] += b[i]; v[3] = fmaf(b[i], b[i], v[3]);
    w[0] += a[i + 1]; w[1] = fmaf(a[i + 1], a[i + 1], w[1]); w[2] += b[i + 1]; w[3] = fmaf(b[i + 1], b[i + 1], w[3]);
  }
#pragma unroll
  for (int e = 0; e < 4; e++) v[e] += w[e];
#pragma unroll
  for (int o = 16; o; o >>= 1) {
#pragma unroll
    for (int e = 0; e < 4; e++) v[e] += __shfl_xor_sync(0xffffffffu, v[e], o);
  }
  const float ma = v[0] * (1.0f / D_), mb = v[2] * (1.0f / D_);
  ra = sc * rsqrtf(fmaxf(fmaf(-ma, ma, v[1] * (1.0f / D_)), 0.f) + 1e-5f);
  rb = sc * rsqrtf(fmaxf(fmaf(-mb, mb, v[3] * (1.0f / D_)), 0.f) + 1e-5f);
  oa = -ma * ra; ob = -mb * rb;
}

__device__ __forceinline__ float tmat(int c, int q, int j) {
  const int ph = q == 1 ? 1024 * j : (q >> 1) * (c + 128 * j) + 512 * (q & 1);
  return __cosf((float)(((ph + 1024) & 2047) - 1024) * (6.283185307179586f / 2048.0f));
}
__device__ __forceinline__ uint32_t line_off(int k1, int kap, int pi, int f) {
  int kd = 64 * k1 + 9 * kap;
  if (kap == 0 && k1 > 4) kd -= 288;
  if (kd >= D_) kd -= D_;
  return pi * 2400 + ((min(kd, D_ - kd) ^ f) << 3);
}

constexpr int JSK = 5;
struct Ring { uint32_t st, ph; };
template <bool G2, class T> __device__ __forceinline__ void ring_next(T& st, T& ph) {
  if (++st == NST) st = 0;
  ph ^= ((G2 ? 0xDu : 0x1u) >> st) & 1;
}
__device__ __forceinline__ uint32_t mapa(uint32_t a, uint32_t cta) { uint32_t r; asm("mapa.shared::cluster.u32 %0, %1, %2;" : "=r"(r) : "r"(a), "r"(cta)); return r; }
__device__ __forceinline__ void arrive_if(uint32_t a, uint32_t p) {
  asm volatile("{\n.reg .pred p;\nsetp.ne.u32 p, %1, 0;\n@p mbarrier.arrive.shared::cluster.b64 _, [%0];\n}" ::"r"(a), "r"(p) : "memory");
}
template <int NA> __device__ __forceinline__ void reg_fence_n(float (&d)[80]) {
#pragma unroll
  for (int i = 0; i < NA; i++) asm volatile("" : "+f"(d[i])::"memory");
}
template <int MODE>
__device__ __forceinline__ void gemm_main(float (&acc)[80], uint32_t da0, uint32_t da1, uint32_t db0, uint32_t db1, int wg, uint32_t rank,
                                          Ring& rg, uint32_t full0, uint32_t rdy) {
  static_assert(JSK == NST - 1, "the held slot is the first one that is not refilled by GEMM1");
  constexpr int NKB = MODE == 3 ? 36 : 32;
  constexpr uint32_t HA = 0x40000040u, HB = MODE == 3 ? 0x40000040u : 0x80000020u;
  constexpr uint32_t KA = 2048 >> 4, KB = MODE == 3 ? (32 >> 4) : (1024 >> 4);
  constexpr int NA = MODE ? 72 : 80;
  const uint32_t t = threadIdx.x & 127;
  const uint32_t eb = mapa(full0 + 8 * NST, rank);
  uint32_t pb = 0, rel = t == 0, prel = 0;
  int n = NKB - JSK;
#pragma unroll 1
  for (int pass = 0;; pass++) {
#pragma unroll 1
    do {
      const uint32_t so = rg.st * (STAGE >> 4);
      mbar_wait(full0 + 8 * rg.st, rg.ph);
      reg_fence_n<NA>(acc);
      wg_fence();
#pragma unroll
      for (int k = 0; k < 4; k++) {
        if (MODE == 0) wgmma_ss<160, 0, 1>(acc, da0 + so + k * KA, HA, db0 + so + k * KB, HB);
        else if (MODE == 3) wgmma_ss<144, 0, 0>(acc, da0 + so + k * KA, HA, db0 + so + k * KB, HB);
        else {
          wgmma_ss<96, 0, 1>(acc, da0 + so + k * KA, HA, db0 + so + k * KB, HB);
          wgmma_ss<48, 48, 1>(acc, da1 + so + k * KA, HA, db1 + so + k * KB, HB);
        }
      }
      wg_commit();
      wg_wait<1>();
      reg_fence_n<NA>(acc);
      arrive_if(pb, prel);
      pb = eb + 8 * rg.st; prel = rel;
      ring_next<MODE == 3>(rg.st, rg.ph);
    } while (--n);
    if (pass == 2 - wg) break;
    n = 1;
    if (pass == 0) {
      if (MODE != 3) prel = rel & wg;
      else { if (t == 1) pb = mapa(rdy, rank ^ 1); prel = t < 2; rel = 0; }
      n = JSK - 1 + wg;
      if (!wg) continue;
      wg_wait<0>();
      arrive_if(pb, prel);
      prel = 0;
    }
    bar_sync(1, 256);
  }
  wg_wait<0>();
  reg_fence_n<NA>(acc);
  if (MODE != 3) arrive_if(pb, prel & ~wg);
}

__device__ __forceinline__ float gelu_arg(float h) { return h * fmaf(8.0f * 0.044715f * 0.7978845608028654f, h * h, 2.0f * 0.7978845608028654f); }

__device__ __forceinline__ int kb2_order(int i) { const int wv = i / 6; return 6 * (i - 6 * wv) + ((0x431250 >> (4 * wv)) & 7); }

__device__ __forceinline__ void wait_flags(const unsigned* base, int n, int idx, unsigned target, uint64_t& ready) {
  if ((ready >> idx) & 1) return;
  const int l = threadIdx.x & 31;
  int it = 0;
  while (true) {
    unsigned a = ld_rlx(base + l), b = l + 32 < n ? ld_rlx(base + l + 32) : target;
    ready = (uint64_t)__ballot_sync(0xffffffffu, (int)(a - target) >= 0) | ((uint64_t)__ballot_sync(0xffffffffu, (int)(b - target) >= 0) << 32);
    if ((ready >> idx) & 1) break;
    if (++it > (1 << 21)) __trap();
  }
  fence_async_glb();
}

enum { B_FULL = 0, B_EMPTY = 6, B_FLT = 12, B_Z1, B_Z2, B_RDY, B_RCV, B_GO, B_S4, B_S5, B_NUM };

__global__ void __launch_bounds__(NTHR, 1)
fused_kernel(const Params p, const __grid_constant__ Maps maps) {
  extern __shared__ uint8_t smem_raw[];
  __shared__ uint64_t bars[B_NUM];
  __shared__ __align__(16) float redbuf[128];

  const uint32_t sbase = (smem_u32(smem_raw) + 1023) & ~1023u;
  const uint32_t full0 = smem_u32(bars), empty0 = full0 + 8 * B_EMPTY, red = smem_u32(redbuf);
  const int tid = threadIdx.x, wg = tid >> 7, cta = blockIdx.x, t128 = tid & 127;
  const int wp = tid >> 5, l = tid & 31, g = l >> 2, t = l & 3;
  const int q = cta >> 1, r = cta & 1;
  Scratch* const sc = p.s;
  const bool rows = cta < 128;
  const int R = cta - 12;

  uint32_t xr[18];
  float sil[9];
  if (wg < 2) {
    if (rows) {
      const uint32_t* xs = reinterpret_cast<const uint32_t*>(p.x) + (size_t)(cta + 256 * wp) * 288 + l;
#pragma unroll
      for (int i = 0; i < 9; i++) { xr[i] = __ldg(xs + 32 * i); xr[9 + i] = __ldg(xs + 128 * 288 + 32 * i); }
    }
  } else {
#pragma unroll
    for (int i = 0; i < 9; i++) sil[i] = __bfloat162float(p.c[(t128 >> 1) + 64 * i]);
  }
  const unsigned ep = ld_rlx(&sc->cnt[C_EP]) + 1;
  CK(0);
  if (tid == 0) {
    TS(0);
#pragma unroll 1
    for (int i = 0; i < B_NUM; i++) mbar_init(full0 + 8 * i, i == B_FLT ? 128 : (i >= B_EMPTY && i < B_FLT) || i == B_RDY ? 2 : 1);
    mbar_expect(full0 + 8 * B_RCV, 18432);
    asm volatile("fence.mbarrier_init.release.cluster;" ::: "memory");
    fence_async_smem();
  }
  if (tid >= 32 && tid < 40) asm volatile("prefetch.tensormap [%0];" ::"l"(&maps.w1a + (tid - 32)) : "memory");
  if (tid == 64 && cta == NCTA - 1) prefetch_l2(p.tab, sizeof(T_TAB));
  __syncwarp();
  asm volatile("barrier.cluster.arrive.relaxed.aligned;" ::: "memory");
  const uint32_t tag16 = ep & 0xffffu, tag1 = ep & 1u;

  if (wg == 2) {
#pragma unroll
    for (int i = 0; i < 9; i++) sil[i] = rbf(__fdividef(sil[i], 1.0f + __expf(-sil[i])));
    if (cta < 72) { mod_unit<9>(p, cta, t128, sil, red, tag16); if (t128 == 0) TS(25); }
    CK(1);
  }
  const int kap = 8 * ((wp & 3) ^ (wg & 1)) + g;
  uint4 af[4];
  if (rows) {
    uint32_t tb[4];
#pragma unroll
    for (int i = 0; i < 4; i++) tb[i] = pack_bf16(tmat(cta, 8 * (i >> 1) + g, 2 * t + 8 * (i & 1)), tmat(cta, 8 * (i >> 1) + g, 2 * t + 8 * (i & 1) + 1));
    if (wg < 2) {
#pragma unroll
      for (int kk = 0; kk < 4; kk++) af[kk] = __ldg(p.tab + TB_F + kk * 128 + (t128 ^ (wg << 5)));
      float a[18], b[18];
#pragma unroll
      for (int i = 0; i < 9; i++) { a[2 * i] = bf_lo(xr[i]); a[2 * i + 1] = bf_hi(xr[i]); b[2 * i] = bf_lo(xr[9 + i]); b[2 * i + 1] = bf_hi(xr[9 + i]); }
      float oa, ra, ob, rb;
      ln_stats2(a, b, 1.0f, oa, ra, ob, rb);
      CK(1);
      const uint32_t sn = sbase + O_NRM + wp * 2336 + l * 4;
#pragma unroll
      for (int i = 0; i < 9; i++) {
        sts(sn + i * 128, pack_bf16(fmaf(a[2 * i], ra, oa), fmaf(a[2 * i + 1], ra, oa)));
        sts(sn + 1168 + i * 128, pack_bf16(fmaf(b[2 * i], rb, ob), fmaf(b[2 * i + 1], rb, ob)));
      }
    }
    CK(2);
    __syncthreads();
    if (tid == 0) TS(2);
    if (tid == 256 || tid == 288) prefetch_l2(reinterpret_cast<const uint8_t*>(tid == 256 ? p.wr : p.wi) + cta * 9248, 9248);
    float rs[3][8];
    uint32_t sb1[3];
#pragma unroll
    for (int i = 0; i < 3; i++) {
      uint32_t a0, a1, a2, a3;
      asm volatile("ldmatrix.sync.aligned.m8n8.x4.trans.shared.b16 {%0,%1,%2,%3}, [%4];" : "=r"(a0), "=r"(a1), "=r"(a2), "=r"(a3)
                   : "r"(sbase + O_NRM + ((l & 7) + 8 * (l >> 4)) * 1168 + (48 * wp + 16 * i + (l & 8)) * 2) : "memory");
      mma16<false>(&rs[i][0], a0, a1, a2, a3, tb[0], tb[1]);
      mma16<false>(&rs[i][4], a0, a1, a2, a3, tb[2], tb[3]);
      const int d = 48 * wp + 16 * i + (l & 15);
      sb1[i] = sbase + O_B1 + (l >> 4) * 9216 + (d % 9) * 1024 + (d & 63) * 16;
    }
    CK(3);
    {
      uint2 ms[3], mc[3];
      const uint32_t* mp = sc->mod + 48 * wp + 2 * g;
      int it = 0;
#pragma unroll 1
      while (true) {
        uint32_t bad = 0;
#pragma unroll
        for (int i = 0; i < 3; i++) { ms[i] = ld_rlx2(mp + 16 * i); mc[i] = ld_rlx2(mp + D_ + 16 * i); }
#pragma unroll
        for (int i = 0; i < 3; i++) {
          ms[i].x ^= tag16; ms[i].y ^= tag16; mc[i].x ^= tag16; mc[i].y ^= tag16;
          bad |= ms[i].x | ms[i].y | mc[i].x | mc[i].y;
        }
        if (!(bad & 0xffffu)) break;
        if (++it > (1 << 20)) __trap();
      }
      __syncwarp();
      CK(4);
      if (tid == 0) TS(3);
#pragma unroll
      for (int i = 0; i < 3; i++) {
        const float c0 = __uint_as_float(mc[i].x), c1 = __uint_as_float(mc[i].y);
        const float s0 = t ? 0.f : __uint_as_float(ms[i].x), s1 = t ? 0.f : __uint_as_float(ms[i].y);
        stmatrix4(sb1[i], pack_bf16(fmaf(rs[i][0], c0, s0), rs[i][1] * c0), pack_bf16(fmaf(rs[i][2], c1, s1), rs[i][3] * c1),
                  pack_bf16(rs[i][4] * c0, rs[i][5] * c0), pack_bf16(rs[i][6] * c1, rs[i][7] * c1));
      }
    }
    fence_async_smem();
    CK(5);
    if (wg == 2) bar_arrive(5, NTHR);
    else {
      const int slot = 4 * (cta & 7) + ((cta >> 4) & 3) + 32 * (2 * (cta >> 6) + ((cta >> 3) & 1));
      uint32_t lo[9];
#pragma unroll
      for (int k1 = 0; k1 < 9; k1++) lo[k1] = sbase + O_Z1 + line_off(k1, kap, 4 * wg + t, cta & 3);
      bar_sync(5, NTHR);
      CK(6);
      float acc[36];
      const uint32_t db = (((sbase + O_B1 + wg * 9216) & 0x3FFFF) >> 4) | ((128 >> 4) << 16);
      wg_fence();
#pragma unroll
      for (int kk = 0; kk < 4; kk++) wgmma_rs_72(acc, af[kk].x, af[kk].y, af[kk].z, af[kk].w, db + kk * 16, 1024 >> 4, kk);
      wg_commit();
      wg_wait<0>();
      reg_fence(acc);
      CK(7);
      float2 za[9], zb[9];
#pragma unroll
      for (int i = 0; i < 9; i++) { za[i] = make_float2(acc[4 * i], acc[4 * i + 2]); zb[i] = make_float2(acc[4 * i + 1], acc[4 * i + 3]); }
      dft9(za); dft9(zb);
      if (kap == 0) {
#pragma unroll
        for (int k = 1; k < 5; k++) {
          float2 a = za[k], b = za[9 - k];
          za[k] = make_float2(a.x + b.x, a.y - b.y); za[9 - k] = make_float2(a.y + b.y, b.x - a.x);
          a = zb[k]; b = zb[9 - k];
          zb[k] = make_float2(a.x + b.x, a.y - b.y); zb[9 - k] = make_float2(a.y + b.y, b.x - a.x);
        }
        sts2(lo[0] + 288 * 8, (pack_bf16(za[0].y, 0.f) & ~1u) | tag1, pack_bf16(zb[0].y, 0.f));
        za[0].y = 0.f; zb[0].y = 0.f;
      }
      __syncwarp();
#pragma unroll
      for (int k1 = 0; k1 < 9; k1++) sts2(lo[k1], (pack_bf16(za[k1].x, za[k1].y) & ~1u) | tag1, pack_bf16(zb[k1].x, zb[k1].y));
      fence_async_smem();
      CK(8);
      bar_sync(2 + wg, 128);
      if (t128 == 0) {
        tma_st2d(&maps.z1, sbase + O_Z1 + wg * 9600, 40 * slot, 60 * wg);
        bulk_commit_wait_read();
        red_add(&sc->cnt[C_Z1 + 32 * wg], 1);
        if (wg == 0) TS(4);
      }
      __syncwarp();
    }
  } else __syncthreads();

  const int pi = R / 15, col0 = 20 * (R - 15 * pi);
  const int xu = DF_ * pi + col0, xv = DF_ * (pi ? 16 - pi : 8) + col0;
  if (wg == 2) {
    if (R >= 0) {
      const int ch = t128 & 3;
#pragma unroll 1
      for (int a = 0; a < 4; a++) {
        const int x0 = (((a & 1) ? xv : xu) & ~7) + 8 * ch;
        const __nv_bfloat16* src = ((a & 2) ? p.wi : p.wr) + x0 + (size_t)(t128 >> 2) * (16 * DF_);
        const uint32_t dst = sbase + O_RAW + a * 10240 + (t128 >> 2) * 80 + ch * 16;
        if (x0 < 16 * DF_) {
#pragma unroll
          for (int i = 0; i < 4; i++) asm volatile("cp.async.cg.shared.global [%0], [%1], 16;" ::"r"(dst + i * 2560), "l"(src + i * (32 * 16 * DF_)) : "memory");
        }
      }
      asm volatile("cp.async.mbarrier.arrive.noinc.shared::cta.b64 [%0];" ::"r"(full0 + 8 * B_FLT) : "memory");
    }
    CK(6);
#pragma unroll 1
    for (int u = 72 + cta, k = 1; u < 216; u += NCTA, k ^= 1) mod_unit<9>(p, u, t128, sil, red + 256 * k, tag16);
    CK(7);
  }
  if (R >= 0) {
    const int ln0 = wg < 2 ? 2 * wp : 8 + wp;
    const int nl = min(wg < 2 ? 2 : 1, DF_ - col0 - ln0);
    uint4 cf[2][4], G[4];
#pragma unroll
    for (int i = 0; i < 4; i++) {
      cf[0][i] = __ldg(p.tab + TB_P2 + i * 32 + l);
      cf[1][i] = __ldg(p.tab + TB_P2 + (pi ? i : 4 + i) * 32 + l);
      G[i] = __ldg(p.tab + TB_P2 + (8 + i) * 32 + l);
    }
    const uint32_t scf = sbase + O_CF + ln0 * 3072 + l * 16;
    mbar_spin(full0 + 8 * B_FLT, 0);
    CK(9);
#pragma unroll 1
    for (int ln = 0; ln < nl; ln++) {
      const int col = col0 + ln0 + ln, k2 = (57 * col) & 63;
      const bool cj = k2 > 32 || (k2 == 32 && col != 288);
      const float nr = ((col & 31) == 0 && col != 0 && col != 288 ? 0.5f : 1.0f) / ((float)S_ * D_), ni = cj ? -nr : nr;
      const float al = pi ? 1.0f : 0.0f, sq = cj ? -al : al;
      const uint32_t su = sbase + O_RAW + ((xu & 7) + ln0 + ln) * 2, sv = sbase + O_RAW + 10240 + ((xv & 7) + ln0 + ln) * 2;
      float o[24];
#pragma unroll
      for (int tt = 0; tt < 4; tt++) {
        const int kc = g + 64 * (tt >> 1) + 16 * t + 8 * (tt & 1);
        const int mu = (cj ? -kc : kc) & 127, mv = (cj ? -kc - 1 : kc - (pi != 0)) & 127;
        const float ur = lds_bf(su + mu * 80) * nr, ui = lds_bf(su + 20480 + mu * 80) * ni;
        const float vr = lds_bf(sv + mv * 80) * nr, vi = lds_bf(sv + 20480 + mv * 80) * ni;
        o[6 * tt] = fmaf(al, vr, ur); o[6 * tt + 1] = fmaf(al, vi, ui);
        o[6 * tt + 2] = sq * (vi - ui); o[6 * tt + 3] = sq * (ur - vr);
        o[6 * tt + 4] = fmaf(al, ur, vr); o[6 * tt + 5] = fmaf(al, ui, vi);
      }
#pragma unroll
      for (int i = 0; i < 6; i++)
        sts4(scf + ln * 3072 + i * 512, __float_as_uint(o[4 * i]), __float_as_uint(o[4 * i + 1]), __float_as_uint(o[4 * i + 2]), __float_as_uint(o[4 * i + 3]));
    }
    CK(10);
    const uint32_t* zin = sc->z1 + (size_t)R * 5120;
    if (tid == 0) {
      wait_cnt(&sc->cnt[C_Z1 + 32 * (pi >> 2)], 128 * ep);
      TS(12);
      mbar_expect(full0 + 8 * B_Z1, 20480);
      bulk_ld(sbase + O_P2, zin, 20480, full0 + 8 * B_Z1);
    }
    mbar_spin(full0 + 8 * B_Z1, 0);
    CK(11);
    if (tid == 0) TS(8);
#pragma unroll 1
    for (int ln = 0; ln < nl; ln++) {
      const uint32_t off = l * 160 + (((ln0 + ln) ^ (g & 3)) << 3);
      uint2 v[4];
#pragma unroll
      for (int i = 0; i < 4; i++) v[i] = lds2(sbase + O_P2 + off + i * 5120);
      if (__builtin_expect(((v[0].x ^ tag1) | (v[1].x ^ tag1) | (v[2].x ^ tag1) | (v[3].x ^ tag1)) & 1, 0)) {
        int it = 0;
        do {
#pragma unroll
          for (int i = 0; i < 4; i++) v[i] = ld_rlx2(reinterpret_cast<const uint8_t*>(zin) + off + i * 5120);
          if (++it > (1 << 20)) __trap();
        } while (((v[0].x ^ tag1) | (v[1].x ^ tag1) | (v[2].x ^ tag1) | (v[3].x ^ tag1)) & 1);
      }
      __syncwarp();
      uint4 co[6];
#pragma unroll
      for (int i = 0; i < 6; i++) co[i] = lds4(scf + ln * 3072 + i * 512);
      float d[4][4];
      uint32_t A[8];
#pragma unroll
      for (int h = 0; h < 2; h++) {
        mma16<false>(d[2 * h], cf[0][0].x, cf[0][0].y, cf[0][0].z, cf[0][0].w, v[h].x, v[2 + h].x);
        mma16<false>(d[2 * h + 1], cf[1][0].x, cf[1][0].y, cf[1][0].z, cf[1][0].w, v[h].y, v[2 + h].y);
      }
#pragma unroll
      for (int h = 0; h < 2; h++)
#pragma unroll
        for (int L = 0; L < 2; L++) {
          const uint4 tw = cf[L][2 + h];
          const float* z = d[2 * h + L];
          const float2 z0 = cmul(make_float2(z[0], z[2]), make_float2(__uint_as_float(tw.x), __uint_as_float(tw.y)));
          const float2 z1 = cmul(make_float2(z[1], z[3]), make_float2(__uint_as_float(tw.z), __uint_as_float(tw.w)));
          A[4 * h + L] = pack_bf16(z0.x, z0.y); A[4 * h + 2 + L] = pack_bf16(z1.x, z1.y);
        }
#pragma unroll
      for (int tt = 0; tt < 4; tt++) {
        mma16<false>(d[tt], A[0], A[1], A[2], A[3], G[tt].x, G[tt].y);
        mma16<true>(d[tt], A[4], A[5], A[6], A[7], G[tt].z, G[tt].w);
      }
#pragma unroll
      for (int tt = 0; tt < 4; tt++) {
        const uint32_t* cw = reinterpret_cast<const uint32_t*>(co) + 6 * tt;
        const float pr = __uint_as_float(cw[0]), pj = __uint_as_float(cw[1]), qr = __uint_as_float(cw[2]), qj = __uint_as_float(cw[3]);
        const float rr = __uint_as_float(cw[4]), rj = __uint_as_float(cw[5]);
        const float ar = d[tt][0], aj = d[tt][1], br = d[tt][2], bj = d[tt][3];
        A[2 * tt] = pack_bf16(fmaf(-qj, bj, fmaf(qr, br, fmaf(-pj, aj, pr * ar))), fmaf(-qj, br, fmaf(-qr, bj, fmaf(-pj, ar, -pr * aj))));
        A[2 * tt + 1] = pack_bf16(fmaf(qj, aj, fmaf(-qr, ar, fmaf(-rj, bj, rr * br))), fmaf(qj, ar, fmaf(qr, aj, fmaf(-rj, br, -rr * bj))));
      }
#pragma unroll
      for (int tt = 0; tt < 4; tt++) {
        mma16<false>(d[tt], A[0], A[1], A[2], A[3], G[tt].x, G[tt].y);
        mma16<true>(d[tt], A[4], A[5], A[6], A[7], G[tt].z, G[tt].w);
      }
#pragma unroll
      for (int h = 0; h < 2; h++)
#pragma unroll
        for (int L = 0; L < 2; L++) {
          const uint4 tw = cf[L][2 + h];
          const float2 z0 = cmul(make_float2(d[2 * h][2 * L], d[2 * h][2 * L + 1]), make_float2(__uint_as_float(tw.x), __uint_as_float(tw.y)));
          const float2 z1 = cmul(make_float2(d[2 * h + 1][2 * L], d[2 * h + 1][2 * L + 1]), make_float2(__uint_as_float(tw.z), __uint_as_float(tw.w)));
          A[4 * h + 2 * L] = movm(pack_bf16(z0.x, z1.x)); A[4 * h + 2 * L + 1] = movm(pack_bf16(z0.y, z1.y));
        }
#pragma unroll
      for (int h = 0; h < 2; h++) {
        mma16<false>(d[0], cf[0][1].x, cf[0][1].y, cf[0][1].y, cf[0][1].z, A[4 * h], A[4 * h + 1]);
        mma16<false>(d[1], cf[1][1].x, cf[1][1].y, cf[1][1].y, cf[1][1].z, A[4 * h + 2], A[4 * h + 3]);
#pragma unroll
        for (int e = 0; e < 2; e++)
          sts2(sbase + O_P2 + off + (2 * h + e) * 5120, (pack_bf16(d[0][e], d[0][2 + e]) & ~1u) | tag1, pack_bf16(d[1][e], d[1][2 + e]));
      }
      CK(12 + ln);
    }
    fence_async_smem();
    if (wp) bar_arrive(6, NTHR);
    else {
      bar_sync(6, NTHR);
      if (l == 0) {
        tma_st2d(&maps.z2, sbase + O_P2, 40 * R, 0);
        bulk_commit_wait_read();
        red_add(&sc->cnt[C_Z2], 1);
        TS(9);
      }
      __syncwarp();
    }
  }

  int gq, gi;
  {
    const int tq = q - 4;
    gq = q < 4 ? 0 : tq < 32 ? (tq & 7) : tq < 60 ? 1 + (tq - 32) % 7 : tq - 54;
    gi = q < 4 ? q : tq < 32 ? (tq >> 3) + (gq == 0 ? 4 : 0) : tq < 60 ? 4 + (tq - 32) / 7 : 8;
  }
  const int j1 = 2 * (8 * gq + (gq == 7) + gi) + r, grp = j1 / 11, m1 = j1 - 11 * grp;
  const bool helper = (m1 & 3) == 3;
  const int f1 = 384 * grp + (helper ? 192 : 128) * (m1 >> 2);
  const int d1 = 160 * (m1 & 3), flip = m1 >= 7;
  const int a1bytes = helper ? 24576 : 16384;
  auto load_a1 = [&](int st, int kb) {
    mbar_expect(full0 + 8 * st, STAGE);
    tma4d_ef(sbase + st * STAGE, helper ? &maps.w1b : &maps.w1a, 4 * kb, f1 >> 6, full0 + 8 * st);
  };

  if (rows) {
#pragma unroll
    for (int kk = 0; kk < 4; kk++) af[kk] = __ldg(p.tab + TB_E + kk * 128 + t128);
    uint32_t tb[4], sy[6];
#pragma unroll
    for (int i = 0; i < 4; i++) tb[i] = pack_bf16(tmat(cta, 2 * t + 8 * (i & 1), 8 * (i >> 1) + g), tmat(cta, 2 * t + 8 * (i & 1) + 1, 8 * (i >> 1) + g));
#pragma unroll
    for (int i = 0; i < 6; i++) {
      const int rr = 16 * (wp & 3) + g + 8 * (i & 1);
      sy[i] = sbase + O_Y + (t * 584 + 64 * ((3 * wg + (i >> 1) + 63 - rr) % 9) + rr) * 4;
    }
    const int slot = 4 * (cta >> 4) + ((cta >> 1) & 3) + 32 * (2 * ((cta >> 3) & 1) + (cta & 1));
    const uint32_t* zin = sc->z2 + (size_t)slot * 4800;
    if (wg == 2) {
#pragma unroll 1
      for (int i = t128; i < 432; i += 128) {
        uint4 v;
        int it = 0;
        while (true) {
          v = ld_rlx4(sc->mod + 2 * D_ + 4 * i);
          v.x ^= tag16; v.y ^= tag16; v.z ^= tag16; v.w ^= tag16;
          if (!((v.x | v.y | v.z | v.w) & 0xffffu)) break;
          if (++it > (1 << 20)) __trap();
        }
        sts4(sbase + O_MOD + 16 * i, v.x, v.y, v.z, v.w);
      }
      __syncwarp();
      CK(14);
      mbar_spin(full0 + 8 * B_Z2, 0);
      if (l == 0) {
        load_a1(wp - 8, wp - 8);
        if (wp > 8 && wp - 8 < NG1) prefetch_l2(reinterpret_cast<const uint8_t*>(p.w1) + (size_t)(128 * (cta >> 3) + 16 * (wp - 8) + 2 * (cta & 7)) * (2 * F_), 4 * F_);
      }
      __syncwarp();
    } else {
      uint32_t lo[9];
#pragma unroll
      for (int k1 = 0; k1 < 9; k1++) lo[k1] = line_off(k1, kap, 4 * wg + t, (cta >> 4) & 3);
      CK(14);
      if (tid == 0) {
        wait_cnt(&sc->cnt[C_Z2], 120 * ep);
        TS(14);
        mbar_expect(full0 + 8 * B_Z2, 19200);
        bulk_ld(sbase + O_IN, zin, 19200, full0 + 8 * B_Z2);
      }
      mbar_spin(full0 + 8 * B_Z2, 0);
      CK(15);
      if (tid == 0) TS(11);
      uint2 v[10];
      const uint32_t lx = lo[0] + (kap ? 0 : 288 * 8);
      uint32_t bad = 0;
#pragma unroll
      for (int k1 = 0; k1 < 10; k1++) { v[k1] = lds2(sbase + O_IN + (k1 < 9 ? lo[k1] : lx)); bad |= v[k1].x ^ tag1; }
      if (__builtin_expect(bad & 1, 0)) {
        int it = 0;
        do {
          bad = 0;
#pragma unroll
          for (int k1 = 0; k1 < 10; k1++) { v[k1] = ld_rlx2(reinterpret_cast<const uint8_t*>(zin) + (k1 < 9 ? lo[k1] : lx)); bad |= v[k1].x ^ tag1; }
          if (++it > (1 << 20)) __trap();
        } while (bad & 1);
      }
      float2 za[9], zb[9];
#pragma unroll
      for (int i = 0; i < 9; i++) { za[i] = make_float2(bf_lo(v[i].x), bf_hi(v[i].x)); zb[i] = make_float2(bf_lo(v[i].y), bf_hi(v[i].y)); }
      if (kap == 0) {
#pragma unroll
        for (int k = 1; k < 5; k++) {
          float2 a = za[k], b = za[9 - k];
          za[k] = make_float2(a.x - b.y, a.y + b.x); za[9 - k] = make_float2(a.x + b.y, b.x - a.y);
          a = zb[k]; b = zb[9 - k];
          zb[k] = make_float2(a.x - b.y, a.y + b.x); zb[9 - k] = make_float2(a.x + b.y, b.x - a.y);
        }
        za[0].y = bf_lo(v[9].x); zb[0].y = bf_lo(v[9].y);
      }
      __syncwarp();
      dft9(za); dft9(zb);
      const uint32_t sb3 = sbase + O_B3 + wg * 1024 + (l >> 4) * 2048 + (2 * (kap & 24) + (l & 15)) * 16;
#pragma unroll
      for (int n = 0; n < 8; n += 2) {
        const int i0 = (9 - n) % 9, i1 = 8 - n;
        stmatrix4(sb3 + n * 2048, pack_bf16(za[i0].x, zb[i0].x), pack_bf16(za[i0].y, zb[i0].y), pack_bf16(za[i1].x, zb[i1].x), pack_bf16(za[i1].y, zb[i1].y));
      }
      stmatrix2(sb3 + 8 * 2048, pack_bf16(za[1].x, zb[1].x), pack_bf16(za[1].y, zb[1].y));
      fence_async_smem();
    }
    CK(16);
    __syncthreads();
    CK(17);
    float acc[24];
    const uint32_t db = (((sbase + O_B3 + wg * 6144) & 0x3FFFF) >> 4) | ((128 >> 4) << 16);
    wg_fence();
#pragma unroll
    for (int kk = 0; kk < 4; kk++) wgmma_rs_48(acc, af[kk].x, af[kk].y, af[kk].z, af[kk].w, db + kk * 16, 1024 >> 4, kk);
    wg_commit();
    uint32_t ga[9];
    uint2 sh[9], sw[9];
    if (wg < 2) {
#pragma unroll
      for (int i = 0; i < 9; i++) {
        const uint2 v = lds2(sbase + O_MOD + (64 * i + 2 * l) * 4);
        ga[i] = __byte_perm(v.x, v.y, 0x7632);
        sh[i] = lds2(sbase + O_MOD + (D_ + 64 * i + 2 * l) * 4);
        sw[i] = lds2(sbase + O_MOD + (2 * D_ + 64 * i + 2 * l) * 4);
      }
    }
    wg_wait<0>();
    reg_fence(acc);
    CK(18);
#pragma unroll
    for (int i = 0; i < 3; i++) {
      const float* a = &acc[8 * i];
      const uint32_t a0 = pack_bf16(a[0], a[1]), a1 = pack_bf16(a[2], a[3]), a2 = pack_bf16(a[4], a[5]), a3 = pack_bf16(a[6], a[7]);
#pragma unroll
      for (int jh = 0; jh < 2; jh++) {
        float y[4];
        mma16<false>(y, a0, a1, a2, a3, tb[2 * jh], tb[2 * jh + 1]);
        sts(sy[2 * i] + jh * (4 * 584 * 4), pack_bf16(y[0], y[1]));
        sts(sy[2 * i + 1] + jh * (4 * 584 * 4), pack_bf16(y[2], y[3]));
      }
    }
    CK(19);
    if (wg == 2) bar_arrive(7, NTHR);
    else {
      bar_sync(7, NTHR);
      CK(20);
      float a[18], b[18];
#pragma unroll
      for (int i = 0; i < 9; i++) {
        const uint2 y = lds2(sbase + O_Y + (wp * 584 + 64 * i + 2 * l) * 4);
        xr[i] = hfma2(ga[i], __byte_perm(y.x, y.y, 0x5410), xr[i]);
        xr[9 + i] = hfma2(ga[i], __byte_perm(y.x, y.y, 0x7632), xr[9 + i]);
        a[2 * i] = bf_lo(xr[i]); a[2 * i + 1] = bf_hi(xr[i]); b[2 * i] = bf_lo(xr[9 + i]); b[2 * i + 1] = bf_hi(xr[9 + i]);
      }
      float oa, ra, ob, rb;
      ln_stats2(a, b, 1.0f, oa, ra, ob, rb);
      CK(21);
#pragma unroll
      for (int i = 0; i < 9; i++) {
        const float c0 = __uint_as_float(sw[i].x), c1 = __uint_as_float(sw[i].y), s0 = __uint_as_float(sh[i].x), s1 = __uint_as_float(sh[i].y);
        a[2 * i] = fmaf(fmaf(a[2 * i], ra, oa), c0, s0); a[2 * i + 1] = fmaf(fmaf(a[2 * i + 1], ra, oa), c1, s1);
        b[2 * i] = fmaf(fmaf(b[2 * i], rb, ob), c0, s0); b[2 * i + 1] = fmaf(fmaf(b[2 * i + 1], rb, ob), c1, s1);
      }
      ln_stats2(a, b, 0.5f, oa, ra, ob, rb);
      CK(22);
      const uint32_t sh3 = sbase + O_IN + (l >> 4) * 1024 + wp * 128 + ((((l >> 2) ^ wp) & 3) << 4) + (l & 3) * 4;
#pragma unroll
      for (int i = 0; i < 9; i++) {
        sts(sh3 + i * 2048, pack_bf16(fmaf(a[2 * i], ra, oa), fmaf(a[2 * i + 1], ra, oa)));
        sts(sh3 + i * 2048 + 64, pack_bf16(fmaf(b[2 * i], rb, ob), fmaf(b[2 * i + 1], rb, ob)));
      }
      fence_async_smem();
      bar_arrive(8, 288);
      CK(23);
      const uint32_t sx = sbase + O_B3 + wp * 2304 + l * 4;
#pragma unroll
      for (int i = 0; i < 9; i++) { sts(sx + i * 128, xr[i]); sts(sx + 1152 + i * 128, xr[9 + i]); }
      fence_async_smem();
      bar_arrive(9, 288);
    }
  } else __syncthreads();
  asm volatile("barrier.cluster.wait.aligned;" ::: "memory");

  const bool g2 = q < 64;
  const int z2 = 8 * gq + gi;
  const int s2 = 128 * (z2 >> 2), d2 = 144 * (z2 & 3);
  const uint32_t rdy = full0 + 8 * B_RDY, rcv = full0 + 8 * B_RCV;
  constexpr int XST = (33 + 36 - JSK - 1) % NST;
  constexpr int ST0 = (32 - JSK - 1) % NST, ST1 = 31 % NST;

  if (wg == 2) {
    asm volatile("setmaxnreg.dec.sync.aligned.u32 40;");
    if (tid == 256) {
      int st = rows ? 4 : 0, ph = 1;
#pragma unroll 1
      for (int kb = st; kb < 32; kb++) {
        if (rows && kb < 6) mbar_spin(full0 + 8 * (B_S4 - 4 + kb), 0);
        mbar_spin(empty0 + 8 * st, ph);
        load_a1(st, kb);
        if (kb >= PF2K && kb < PF2K + PF2 && g2)
          prefetch_l2(reinterpret_cast<const uint8_t*>(p.w2) + (size_t)(36 * r + kb2_order(kb - PF2K)) * 262144 + q * 4096, 4096);
        ring_next<false>(st, ph);
      }
      if (g2) {
        st++;
#pragma unroll 1
        for (int i = 0; i < 36; i++) {
          if (i == HOLDA) mbar_spin(full0 + 8 * B_GO, 0);
          mbar_spin(empty0 + 8 * st, ph);
          mbar_expect(full0 + 8 * st, 16384 + 18432);
          tma3d_ef(sbase + st * STAGE, &maps.w2, 64 * (36 * r + kb2_order(i)), s2 >> 6, full0 + 8 * st);
          ring_next<true>(st, ph);
        }
      }
    } else if (wp >= 10) {
      const int sw = wp - 10;
      if (rows) {
        bar_sync(9 - sw, 288);
        if (l == 0) {
          if (sw) {
            tma_st2d(&maps.h3, sbase + O_IN, 256 * (cta & 3), 18 * (cta >> 2));
            bulk_commit_wait();
            TS(1);
            mbar_arrive(full0 + 8 * B_S4);
            asm volatile("fence.acq_rel.gpu;" ::: "memory");
            red_add(&sc->cnt[C_H3 + (cta >> 2)], 1);
            TS(13);
          } else {
            mbar_spin(full0, 0);
#pragma unroll 1
            for (int j = 0; j < 16; j++) bulk_st(sc->x1 + (size_t)(cta + 128 * j) * 288, sbase + O_B3 + j * 1152, 1152);
            bulk_commit_wait();
            mbar_arrive(full0 + 8 * B_S5);
          }
        }
        __syncwarp();
      }
      const uint32_t stg = sbase + (sw ? ST1 : ST0) * STAGE;
      const int kbA = (f1 >> 6) + (helper ? 2 : 1) * (sw ^ flip), kbB = helper ? (f1 >> 6) + 1 : kbA;
      const int dB = helper ? d1 + 32 * sw : d1 + 96;
      bar_sync(11 + sw, 160);
      if (l == 0) { TS(sw ? 31 : 30); bulk_st(sc->u + ((size_t)kbA * D_ + d1) * 128, stg, 96 * 128); }
      __syncwarp();
      bar_sync(13 + sw, 160);
      if (l == 0) {
        bulk_st(sc->u + ((size_t)kbB * D_ + dB) * 128, stg + 96 * 128, helper ? 32 * 128 : 64 * 128);
        if (helper) bulk_st(sc->u + ((size_t)kbB * D_ + d1 + 64 + 16 * sw) * 128, stg + 128 * 128, 16 * 128);
        bulk_commit_wait();
        mbar_arrive(empty0 + 8 * (sw ? ST1 : ST0));
        if (sw == 0) TS(26);
        asm volatile("fence.acq_rel.gpu;" ::: "memory");
        red_add(&sc->cnt[C_U + kbA], 2);
        if (helper) red_add(&sc->cnt[C_U + kbB], 1);
        TS(sw ? 23 : 17);
      }
    } else if (wp == 9) {
      uint64_t ready = 0;
      int st = 0, ph = 1;
#pragma unroll 1
      for (int kb = 0; kb < 32; kb++) {
        if (rows && (kb >> 1) == 2) mbar_spin(full0 + 8 * (B_S4 - 4 + kb), 0);
        mbar_spin(empty0 + 8 * st, ph);
        wait_flags(sc->cnt + C_H3, 32, kb, 4 * ep, ready);
        if (l == 0) bulk_ld(sbase + st * STAGE + a1bytes, sc->h3 + ((size_t)(kb * 18 + (d1 >> 5)) << 12), STAGE - a1bytes, full0 + 8 * st);
        ring_next<false>(st, ph);
      }
      if (g2) {
        ready = 0;
        st++;
#pragma unroll 1
        for (int i = 0; i < 72; i++) {
          if (i == 36) ready = 0;
          const int kb = kb2_order(i < 36 ? i : i - 36), hf = r ^ (i >= 36);
          if (i <= 36) mbar_spin(empty0 + 8 * st, ph);
          wait_flags(sc->cnt + C_U + 36 * hf, 36, kb, 8 * ep, ready);
          if (i < 36) {
            if (l == 0) {
              bulk_ld(sbase + st * STAGE + 16384, sc->u + ((size_t)(36 * r + kb) * D_ + d2) * 128, 18432, full0 + 8 * st);
              if (i == GOAT) mbar_arrive(full0 + 8 * B_GO);
            }
            ring_next<true>(st, ph);
          } else if (ready == ~0ull) break;
        }
        if (l == 0) mbar_expect(full0 + 8 * XST, 18432);
        __syncwarp();
        if (l < 3) tma2d(sbase + XST * STAGE + 18432 + l * 6144, &maps.x1, d2 + 48 * l, s2 + 64 * (r ^ 1), full0 + 8 * XST);
      }
    }
  } else {
    asm volatile("setmaxnreg.inc.sync.aligned.u32 232;");
    const int wgu = __shfl_sync(0xffffffffu, wg, 0);
    const uint32_t sb4 = __shfl_sync(0xffffffffu, (sbase & 0x3FFFF) >> 4, 0), fullu = __shfl_sync(0xffffffffu, full0, 0);
    const int w = wp & 3;
    Ring rg = {0, 0};
    float acc[80];
    constexpr uint32_t LA = (8192 >> 4) << 16, LB = (4096 >> 4) << 16;
    {
      const int fa = f1 + (helper ? 128 : 64) * (wg ^ flip) + 16 * w + g, fb = helper ? f1 + 64 + 16 * w + g : fa;
      const float a0 = 0.5f * __bfloat162float(p.b1[fa]), a1 = 0.5f * __bfloat162float(p.b1[fa + 8]);
      const float b0 = 0.5f * __bfloat162float(p.b1[fb]), b1 = 0.5f * __bfloat162float(p.b1[fb + 8]);
#pragma unroll
      for (int i = 0; i < 80; i++) acc[i] = i < 48 ? ((i & 2) ? a1 : a0) : ((i & 2) ? b1 : b0);
      reg_fence(acc);
    }
    if (!helper) gemm_main<0>(acc, sb4 + (wgu ^ flip) * 512 + LA, 0, sb4 + 1024 + LB, 0, wgu, r, rg, fullu, rdy);
    else {
      float ac2[80];
#pragma unroll
      for (int i = 0; i < 72; i++) asm volatile("mov.b32 %0, %1;" : "=f"(ac2[i]) : "f"(acc[i]));
      gemm_main<1>(ac2, sb4 + (wgu ^ flip) * 1024 + LA, sb4 + 512 + LA, sb4 + 1536 + LB, sb4 + 1536 + (wgu ? 256 + LB + (2 << 16) : 2 * LB), wgu, r, rg, fullu, rdy);
#pragma unroll
      for (int i = 0; i < 72; i++) asm volatile("mov.b32 %0, %1;" : "=f"(acc[i]) : "f"(ac2[i]));
    }
    if (t128 == 0) TS(wg ? 16 : 6);
    {
      const int mi = l >> 3, rr = l & 7;
      const uint32_t ad = sbase + (wg ? ST1 : ST0) * STAGE + (8 * (mi >> 1) + rr) * 128 + (((2 * w + (mi & 1)) ^ rr) << 4);
      float z[2][16];
#pragma unroll
      for (int j = -1; j <= 5; j++) {
        if (j >= 1) {
          const float* a = &acc[16 * (j - 1)];
          const float* tt = z[(j - 1) & 1];
#pragma unroll
          for (int h = 0; h < 16; h += 8)
            stmatrix4t(ad + (2 * (j - 1) + (h >> 3)) * 2048, pack_bf16(fmaf(a[h], tt[h], a[h]), fmaf(a[h + 1], tt[h + 1], a[h + 1])),
                       pack_bf16(fmaf(a[h + 2], tt[h + 2], a[h + 2]), fmaf(a[h + 3], tt[h + 3], a[h + 3])),
                       pack_bf16(fmaf(a[h + 4], tt[h + 4], a[h + 4]), fmaf(a[h + 5], tt[h + 5], a[h + 5])),
                       pack_bf16(fmaf(a[h + 6], tt[h + 6], a[h + 6]), fmaf(a[h + 7], tt[h + 7], a[h + 7])));
        }
        if (j >= 0 && j < 5) {
#pragma unroll
          for (int e = 0; e < 16; e++) asm("tanh.approx.f32 %0, %0;" : "+f"(z[j & 1][e]));
        }
        if (j < 4) {
#pragma unroll
          for (int e = 0; e < 16; e++) z[(j + 1) & 1][e] = gelu_arg(acc[16 * (j + 1) + e]);
        }
        if (j == 3 || j == 5) { fence_async_smem(); asm volatile("bar.arrive %0, 160;" ::"r"((j == 3 ? 11 : 13) + wgu) : "memory"); }
        if (j < 5) {
          if (j >= 0) reg_fence(z[j & 1]);
          if (j < 4) reg_fence(z[(j + 1) & 1]);
          if (__builtin_expect(ad == 0x7ffffff0u + j, 0)) __trap();
          reg_fence(acc);
        }
      }
      if (t128 == 0) TS(wg ? 29 : 28);
    }
    if (g2) {
      const int mb = wgu ^ r;
      uint32_t gb[18];
      {
        float a0 = 0.f, a1 = 0.f;
        if (wgu) {
          a0 = __bfloat162float(p.b2[s2 + 64 * mb + 16 * w + g]); a1 = __bfloat162float(p.b2[s2 + 64 * mb + 16 * w + 8 + g]);
          int it = 0;
          uint32_t bad;
          do {
            bad = 0;
#pragma unroll
            for (int i = 0; i < 18; i++) {
              const uint2 v = ld_rlx2(sc->mod + 5 * D_ + d2 + 8 * i + 2 * t);
              bad |= (v.x ^ tag16) | (v.y ^ tag16);
              gb[i] = __byte_perm(v.x, v.y, 0x7632);
            }
            if (++it > (1 << 20)) __trap();
          } while (bad & 0xffffu);
          __syncwarp();
        }
#pragma unroll
        for (int i = 0; i < 72; i++) acc[i] = (i & 2) ? a1 : a0;
      }
      rg.st++;
      gemm_main<3>(acc, sb4 + mb * 512 + LA, 0, sb4 + 1024 + (1 << 16), 0, wgu, r, rg, fullu, rdy);
      if (t128 == 0) TS(wg ? 20 : 19);
      const uint32_t sx = sbase + XST * STAGE;
      if (wgu == 0) {
        uint32_t rx, rb;
        asm("mapa.shared::cluster.u32 %0, %1, %2;" : "=r"(rx) : "r"(sx + t128 * 16), "r"(r ^ 1));
        asm("mapa.shared::cluster.u32 %0, %1, %2;" : "=r"(rb) : "r"(rcv), "r"(r ^ 1));
        mbar_wait_cluster(rdy, 0);
#pragma unroll
        for (int j = 0; j < 9; j++) {
          const float* a = &acc[8 * j];
          asm volatile("st.async.weak.shared::cluster.mbarrier::complete_tx::bytes.v4.b32 [%0], {%1,%2,%3,%4}, [%5];" ::"r"(rx + j * 2048),
                       "r"(pack_bf16(a[0], a[1])), "r"(pack_bf16(a[2], a[3])), "r"(pack_bf16(a[4], a[5])), "r"(pack_bf16(a[6], a[7])), "r"(rb) : "memory");
        }
        if (tid == 0) TS(21);
        if (w == 0) {
#pragma unroll 1
          for (int i = 0; i < 3; i++) {
            bar_sync(11 + i, 160);
            if (l == 0) tma_st2d(&maps.out, sx + 18432 + i * 6144, d2 + 48 * i, s2 + 64 * (r ^ 1));
            __syncwarp();
          }
          if (l == 0) { bulk_commit_wait_read(); TS(22); }
        }
      } else {
        mbar_wait(fullu + 8 * XST, rg.ph);
        mbar_wait_cluster(rcv, 0);
        if (t128 == 0) TS(5);
        if (tid == 128 && cta == 0) sc->cnt[C_EP] = ep;
        const uint32_t xa = sx + 18432 + (16 * w + (l & 15)) * 96 + (l >> 4) * 16;
#pragma unroll
        for (int c = 0; c < 3; c++) {
          uint32_t pv[3][4], xv[3][4];
#pragma unroll
          for (int j = 0; j < 3; j++) {
            asm volatile("ld.shared.v4.b32 {%0,%1,%2,%3}, [%4];" : "=r"(pv[j][0]), "=r"(pv[j][1]), "=r"(pv[j][2]), "=r"(pv[j][3]) : "r"(sx + t128 * 16 + (3 * c + j) * 2048) : "memory");
            asm volatile("ldmatrix.sync.aligned.m8n8.x4.shared.b16 {%0,%1,%2,%3}, [%4];" : "=r"(xv[j][0]), "=r"(xv[j][1]), "=r"(xv[j][2]), "=r"(xv[j][3]) : "r"(xa + c * 6144 + j * 32) : "memory");
          }
#pragma unroll
          for (int j = 0; j < 3; j++) {
            const float* a = &acc[8 * (3 * c + j)];
            uint32_t o[4];
#pragma unroll
            for (int e = 0; e < 4; e++)
              o[e] = hadd2(xv[j][e], hmul2(gb[2 * (3 * c + j) + (e >> 1)], pack_bf16(a[2 * e] + bf_lo(pv[j][e]), a[2 * e + 1] + bf_hi(pv[j][e]))));
            stmatrix4(xa + c * 6144 + j * 32, o[0], o[1], o[2], o[3]);
          }
          fence_async_smem();
          asm volatile("bar.arrive %0, 160;" ::"r"(11 + c) : "memory");
        }
        if (t128 == 0) TS(7);
      }
    }
  }
}

typedef CUresult (*EncodeFn)(CUtensorMap*, CUtensorMapDataType, cuuint32_t, void*, const cuuint64_t*, const cuuint64_t*, const cuuint32_t*,
                             const cuuint32_t*, CUtensorMapInterleave, CUtensorMapSwizzle, CUtensorMapL2promotion, CUtensorMapFloatOOBfill);

struct Dim { cuuint64_t n, stride; cuuint32_t box; };
template <int RANK>
void make_map(EncodeFn enc, CUtensorMap* m, bool words, bool swz, const void* ptr, const Dim (&d)[RANK]) {
  cuuint64_t gd[RANK], gs[RANK];
  cuuint32_t bx[RANK], es[RANK];
  for (int i = 0; i < RANK; i++) { gd[i] = d[i].n; gs[i] = d[i].stride; bx[i] = d[i].box; es[i] = 1; }
  enc(m, words ? CU_TENSOR_MAP_DATA_TYPE_UINT32 : CU_TENSOR_MAP_DATA_TYPE_BFLOAT16, RANK, const_cast<void*>(ptr), gd, gs + 1, bx, es,
      CU_TENSOR_MAP_INTERLEAVE_NONE, swz ? CU_TENSOR_MAP_SWIZZLE_128B : CU_TENSOR_MAP_SWIZZLE_NONE,
      swz ? CU_TENSOR_MAP_L2_PROMOTION_L2_256B : CU_TENSOR_MAP_L2_PROMOTION_NONE, CU_TENSOR_MAP_FLOAT_OOB_FILL_NONE);
}

}

extern "C" void kernel_launch(void* const* d_in, const int* in_sizes, int n_in, void* d_out, int out_size) {
  (void)in_sizes; (void)n_in; (void)out_size;
  static EncodeFn enc = nullptr;
  static void *sptr = nullptr, *tptr = nullptr;
  if (!enc) {
    void* f = nullptr; cudaDriverEntryPointQueryResult qr;
    cudaGetDriverEntryPoint("cuTensorMapEncodeTiled", &f, cudaEnableDefault, &qr);
    enc = reinterpret_cast<EncodeFn>(f);
    cudaFuncSetAttribute(fused_kernel, cudaFuncAttributeMaxDynamicSharedMemorySize, SMEM_BYTES);
    cudaGetSymbolAddress(&sptr, g_s);
    cudaGetSymbolAddress(&tptr, T_TAB);
  }
  Params p;
  p.x = (const __nv_bfloat16*)d_in[0]; p.wr = (const __nv_bfloat16*)d_in[1]; p.wi = (const __nv_bfloat16*)d_in[2];
  p.b1 = (const __nv_bfloat16*)d_in[5]; p.b2 = (const __nv_bfloat16*)d_in[7];
  p.c = (const __nv_bfloat16*)d_in[8]; p.wmod = (const __nv_bfloat16*)d_in[9];
  p.w1 = (const __nv_bfloat16*)d_in[4]; p.w2 = (const __nv_bfloat16*)d_in[6];
  p.s = static_cast<Scratch*>(sptr); p.tab = static_cast<const uint4*>(tptr);
  Maps maps;
  make_map<4>(enc, &maps.w1a, false, true, p.w1, {{64, 0, 64}, {16, 128 * 2 * F_, 16}, {128, 2 * F_, 4}, {72, 128, 2}});
  make_map<4>(enc, &maps.w1b, false, true, p.w1, {{64, 0, 64}, {16, 128 * 2 * F_, 16}, {128, 2 * F_, 4}, {72, 128, 3}});
  make_map<3>(enc, &maps.w2, false, true, p.w2, {{64, 0, 64}, {F_, 2 * S_, 64}, {32, 128, 2}});
  make_map<2>(enc, &maps.x1, false, false, p.s->x1, {{D_, 0, 48}, {S_, 2 * D_, 64}});
  make_map<2>(enc, &maps.out, false, false, d_out, {{D_, 0, 48}, {S_, 2 * D_, 64}});
  make_map<2>(enc, &maps.z1, true, false, p.s->z1, {{5120, 0, 40}, {120, 20480, 60}});
  make_map<2>(enc, &maps.z2, true, false, p.s->z2, {{4800, 0, 40}, {128, 19200, 128}});
  make_map<2>(enc, &maps.h3, true, false, p.s->h3, {{1024, 0, 256}, {32 * 18, 4096, 18}});
  cudaLaunchConfig_t cfg = {};
  cfg.gridDim = dim3(NCTA); cfg.blockDim = dim3(NTHR); cfg.dynamicSmemBytes = SMEM_BYTES; cfg.stream = cudaStreamPerThread;
  cudaLaunchAttribute at[1];
  at[0].id = cudaLaunchAttributeClusterDimension; at[0].val.clusterDim.x = 2; at[0].val.clusterDim.y = 1; at[0].val.clusterDim.z = 1;
  cfg.attrs = at; cfg.numAttrs = 1;
  cudaLaunchKernelEx(&cfg, fused_kernel, p, maps);
}
```

```cpp
#include <cuda_runtime.h>
#include <cuda_bf16.h>
#include <cuda.h>
#include <stdint.h>

namespace {

constexpr int S_ = 2048, D_ = 576, DF_ = 289, F_ = 4608;
constexpr int NCTA = 132, NTHR = 384;
constexpr int STAGE = 36864, NST = 6;
constexpr int SMEM_BYTES = NST * STAGE + 1024;
constexpr int O_NRM = 0, O_B1 = 19456, O_Z1 = 38912, O_P2 = 59392, O_CF = 79872;
constexpr int O_RAW = 4 * STAGE;
constexpr int O_IN = 4 * STAGE, O_Y = O_IN + 19456, O_B3 = O_IN + 38912, O_MOD = O_IN + 57344;

__device__ __align__(128) const uint32_t T_TAB[5632] = {
0x3f803f80,0xbf803f80,0x3f803f80,0xbf803f80,0x3f803f80,0xbf803f80,0x3f803f80,0xbf803f80,0x3f803f80,0xbf803f80,0x3f803f80,0xbf803f80,
0x3f803f80,0xbf803f80,0x3f803f80,0xbf803f80,0x3f7f3f80,0xbdc90000,0x3f223f35,0xbf46bf35,0x3f753f7b,0xbe95be48,0x3ef13f0e,0xbf62bf55,
0x3f623f6d,0xbef1bec4,0x3e953ec4,0xbf75bf6d,0x3f463f55,0xbf22bf0e,0x3dc93e48,0xbf7fbf7b,0x3f7b3f80,0xbe480000,0xbe480000,0xbf7bbf80,
0x3f553f6d,0xbf0ebec4,0xbf0ebec4,0xbf55bf6d,0x3f0e3f35,0xbf55bf35,0xbf55bf35,0xbf0ebf35,0x3e483ec4,0xbf7bbf6d,0xbf7bbf6d,0xbe48bec4,
0x3f753f80,0xbe950000,0xbf62bf35,0xbef1bf35,0x3f223f55,0xbf46bf0e,0xbf7fbf7b,0x3dc9be48,0x3dc93ec4,0xbf7fbf6d,0xbf46bf6d,0x3f223ec4,
0xbef1be48,0xbf62bf7b,0xbe95bf0e,0x3f753f55,0x3f6d3f80,0xbec40000,0xbf6dbf80,0x3ec40000,0x3ec43f35,0xbf6dbf35,0xbec4bf35,0x3f6d3f35,
0xbec40000,0xbf6dbf80,0x3ec40000,0x3f6d3f80,0xbf6dbf35,0xbec4bf35,0x3f6d3f35,0x3ec43f35,0x3f623f80,0xbef10000,0xbe95bf35,0x3f753f35,
0x3dc93f0e,0xbf7fbf55,0x3f223e48,0x3f463f7b,0xbf46bec4,0xbf22bf6d,0x3f7f3f6d,0xbdc93ec4,0xbf75bf7b,0x3e95be48,0x3ef13f55,0xbf62bf0e,
0x3f553f80,0xbf0e0000,0x3f0e0000,0x3f553f80,0xbe483ec4,0xbf7bbf6d,0x3f7b3f6d,0xbe483ec4,0xbf7bbf35,0xbe48bf35,0x3e483f35,0xbf7bbf35,
0xbf0ebf6d,0x3f553ec4,0xbf55bec4,0xbf0ebf6d,0x3f463f80,0xbf220000,0x3f7f3f35,0x3dc93f35,0xbef13e48,0xbf62bf7b,0x3e953f55,0xbf75bf0e,
0xbf75bf6d,0x3e95bec4,0xbf62bec4,0xbef1bf6d,0x3dc9bf0e,0x3f7f3f55,0xbf22bf7b,0x3f463e48,0x3f353f80,0xbf350000,0x3f353f80,0xbf350000,
0xbf350000,0xbf35bf80,0xbf350000,0xbf35bf80,0xbf35bf80,0x3f350000,0xbf35bf80,0x3f350000,0x3f350000,0x3f353f80,0x3f350000,0x3f353f80,
0x3f223f80,0xbf460000,0xbdc93f35,0xbf7fbf35,0xbf62be48,0xbef1bf7b,0xbf75bf55,0x3e95bf0e,0xbe95bf6d,0x3f753ec4,0x3ef1bec4,0x3f623f6d,
0x3f7f3f0e,0x3dc93f55,0x3f463f7b,0xbf223e48,0x3f0e3f80,0xbf550000,0xbf550000,0xbf0ebf80,0xbf7bbec4,0xbe48bf6d,0xbe48bf6d,0x3f7b3ec4,
0x3e48bf35,0x3f7b3f35,0x3f7b3f35,0xbe483f35,0x3f553f6d,0xbf0e3ec4,0xbf0e3ec4,0xbf55bf6d,0x3ef13f80,0xbf620000,0xbf75bf35,0x3e95bf35,
0xbf7fbf0e,0x3dc9bf55,0x3f46be48,0x3f223f7b,0x3f22bec4,0x3f463f6d,0x3dc93f6d,0xbf7fbec4,0x3e953f7b,0xbf75be48,0xbf62bf55,0x3ef1bf0e,
0x3ec43f80,0xbf6d0000,0xbec4bf80,0x3f6d0000,0xbf6dbf35,0x3ec4bf35,0x3f6d3f35,0xbec43f35,0x3f6d0000,0x3ec43f80,0xbf6d0000,0xbec4bf80,
0xbec43f35,0xbf6dbf35,0x3ec4bf35,0x3f6d3f35,0x3e953f80,0xbf750000,0x3ef1bf35,0x3f623f35,0xbf46bf55,0x3f22bf0e,0x3dc93f7b,0xbf7fbe48,
0x3f7f3ec4,0xbdc93f6d,0xbf22bf6d,0x3f46bec4,0xbf623e48,0xbef1bf7b,0x3f753f0e,0xbe953f55,0x3e483f80,0xbf7b0000,0x3f7b0000,0x3e483f80,
0xbf0ebf6d,0x3f55bec4,0xbf553ec4,0xbf0ebf6d,0x3f553f35,0xbf0e3f35,0x3f0ebf35,0x3f553f35,0xbf7bbec4,0x3e48bf6d,0xbe483f6d,0xbf7bbec4,
0x3dc93f80,0xbf7f0000,0x3f463f35,0xbf223f35,0xbe95bf7b,0x3f75be48,0xbf62bf0e,0x3ef1bf55,0x3ef13f6d,0xbf623ec4,0x3f753ec4,0xbe953f6d,
0xbf22bf55,0x3f46bf0e,0xbf7fbe48,0x3dc9bf7b,0x3f80,0xbf800000,0x3f80,0xbf800000,0xbf80,0x3f800000,0xbf80,0x3f800000,
0x3f80,0xbf800000,0x3f80,0xbf800000,0xbf80,0x3f800000,0xbf80,0x3f800000,0xbdc93f80,0xbf7f0000,0xbf463f35,0xbf22bf35,
0x3e95bf7b,0x3f753e48,0x3f62bf0e,0x3ef13f55,0xbef13f6d,0xbf62bec4,0xbf753ec4,0xbe95bf6d,0x3f22bf55,0x3f463f0e,0x3f7fbe48,0x3dc93f7b,
0xbe483f80,0xbf7b0000,0xbf7b0000,0x3e48bf80,0x3f0ebf6d,0x3f553ec4,0x3f553ec4,0xbf0e3f6d,0xbf553f35,0xbf0ebf35,0xbf0ebf35,0x3f55bf35,
0x3f7bbec4,0x3e483f6d,0x3e483f6d,0xbf7b3ec4,0xbe953f80,0xbf750000,0xbef1bf35,0x3f62bf35,0x3f46bf55,0x3f223f0e,0xbdc93f7b,0xbf7f3e48,
0xbf7f3ec4,0xbdc9bf6d,0x3f22bf6d,0x3f463ec4,0x3f623e48,0xbef13f7b,0xbf753f0e,0xbe95bf55,0xbec43f80,0xbf6d0000,0x3ec4bf80,0x3f6d0000,
0x3f6dbf35,0x3ec43f35,0xbf6d3f35,0xbec4bf35,0xbf6d0000,0x3ec4bf80,0x3f6d0000,0xbec43f80,0x3ec43f35,0xbf6d3f35,0xbec4bf35,0x3f6dbf35,
0xbef13f80,0xbf620000,0x3f75bf35,0x3e953f35,0x3f7fbf0e,0x3dc93f55,0xbf46be48,0x3f22bf7b,0xbf22bec4,0x3f46bf6d,0xbdc93f6d,0xbf7f3ec4,
0xbe953f7b,0xbf753e48,0x3f62bf55,0x3ef13f0e,0xbf0e3f80,0xbf550000,0x3f550000,0xbf0e3f80,0x3f7bbec4,0xbe483f6d,0x3e48bf6d,0x3f7bbec4,
0xbe48bf35,0x3f7bbf35,0xbf7b3f35,0xbe48bf35,0xbf553f6d,0xbf0ebec4,0x3f0e3ec4,0xbf553f6d,0xbf223f80,0xbf460000,0x3dc93f35,0xbf7f3f35,
0x3f62be48,0xbef13f7b,0x3f75bf55,0x3e953f0e,0x3e95bf6d,0x3f75bec4,0xbef1bec4,0x3f62bf6d,0xbf7f3f0e,0x3dc9bf55,0xbf463f7b,0xbf22be48,
0xbf353f80,0xbf350000,0xbf353f80,0xbf350000,0x3f350000,0xbf353f80,0x3f350000,0xbf353f80,0x3f35bf80,0x3f350000,0x3f35bf80,0x3f350000,
0xbf350000,0x3f35bf80,0xbf350000,0x3f35bf80,0xbf463f80,0xbf220000,0xbf7f3f35,0x3dc9bf35,0x3ef13e48,0xbf623f7b,0xbe953f55,0xbf753f0e,
0x3f75bf6d,0x3e953ec4,0x3f62bec4,0xbef13f6d,0xbdc9bf0e,0x3f7fbf55,0x3f22bf7b,0x3f46be48,0xbf553f80,0xbf0e0000,0xbf0e0000,0x3f55bf80,
0x3e483ec4,0xbf7b3f6d,0xbf7b3f6d,0xbe48bec4,0x3f7bbf35,0xbe483f35,0xbe483f35,0xbf7b3f35,0x3f0ebf6d,0x3f55bec4,0x3f55bec4,0xbf0e3f6d,
0xbf623f80,0xbef10000,0x3e95bf35,0x3f75bf35,0xbdc93f0e,0xbf7f3f55,0xbf223e48,0x3f46bf7b,0x3f46bec4,0xbf223f6d,0xbf7f3f6d,0xbdc9bec4,
0x3f75bf7b,0x3e953e48,0xbef13f55,0xbf623f0e,0xbf6d3f80,0xbec40000,0x3f6dbf80,0x3ec40000,0xbec43f35,0xbf6d3f35,0x3ec4bf35,0x3f6dbf35,
0x3ec40000,0xbf6d3f80,0xbec40000,0x3f6dbf80,0x3f6dbf35,0xbec43f35,0xbf6d3f35,0x3ec4bf35,0xbf753f80,0xbe950000,0x3f62bf35,0xbef13f35,
0xbf223f55,0xbf463f0e,0x3f7fbf7b,0x3dc93e48,0xbdc93ec4,0xbf7f3f6d,0x3f46bf6d,0x3f22bec4,0x3ef1be48,0xbf623f7b,0x3e95bf0e,0x3f75bf55,
0xbf7b3f80,0xbe480000,0x3e480000,0xbf7b3f80,0xbf553f6d,0xbf0e3ec4,0x3f0ebec4,0xbf553f6d,0xbf0e3f35,0xbf553f35,0x3f55bf35,0xbf0e3f35,
0xbe483ec4,0xbf7b3f6d,0x3f7bbf6d,0xbe483ec4,0xbf7f3f80,0xbdc90000,0xbf223f35,0xbf463f35,0xbf753f7b,0xbe953e48,0xbef13f0e,0xbf623f55,
0xbf623f6d,0xbef13ec4,0xbe953ec4,0xbf753f6d,0xbf463f55,0xbf223f0e,0xbdc93e48,0xbf7f3f7b,0x3f803f80,0xbf803f80,0x3f803f80,0xbf803f80,
0x3f803f80,0xbf803f80,0x3f803f80,0xbf803f80,0x3f803f80,0xbf803f80,0x3f803f80,0xbf803f80,0x3f803f80,0xbf803f80,0x3f803f80,0xbf803f80,
0xbdc90000,0xbf7fbf80,0xbf46bf35,0xbf22bf35,0xbe95be48,0xbf75bf7b,0xbf62bf55,0xbef1bf0e,0xbef1bec4,0xbf62bf6d,0xbf75bf6d,0xbe95bec4,
0xbf22bf0e,0xbf46bf55,0xbf7fbf7b,0xbdc9be48,0xbf7bbf80,0x3e480000,0x3e480000,0x3f7b3f80,0xbf55bf6d,0x3f0e3ec4,0x3f0e3ec4,0x3f553f6d,
0xbf0ebf35,0x3f553f35,0x3f553f35,0x3f0e3f35,0xbe48bec4,0x3f7b3f6d,0x3f7b3f6d,0x3e483ec4,0x3e950000,0x3f753f80,0x3ef13f35,0xbf62bf35,
0x3f463f0e,0x3f223f55,0xbdc93e48,0xbf7fbf7b,0x3f7f3f6d,0x3dc93ec4,0xbf22bec4,0xbf46bf6d,0x3f623f7b,0xbef1be48,0xbf75bf55,0xbe95bf0e,
0x3f6d3f80,0xbec40000,0xbf6dbf80,0x3ec40000,0x3ec43f35,0xbf6dbf35,0xbec4bf35,0x3f6d3f35,0xbec40000,0xbf6dbf80,0x3ec40000,0x3f6d3f80,
0xbf6dbf35,0xbec4bf35,0x3f6d3f35,0x3ec43f35,0xbef10000,0xbf62bf80,0x3f753f35,0x3e953f35,0xbf7fbf55,0xbdc9bf0e,0x3f463f7b,0xbf22be48,
0xbf22bf6d,0x3f463ec4,0xbdc93ec4,0xbf7fbf6d,0x3e95be48,0x3f753f7b,0xbf62bf0e,0xbef1bf55,0xbf55bf80,0x3f0e0000,0xbf0e0000,0xbf55bf80,
0x3e48bec4,0x3f7b3f6d,0xbf7bbf6d,0x3e48bec4,0x3f7b3f35,0x3e483f35,0xbe48bf35,0x3f7b3f35,0x3f0e3f6d,0xbf55bec4,0x3f553ec4,0x3f0e3f6d,
0x3f220000,0x3f463f80,0xbdc9bf35,0x3f7f3f35,0x3f623f7b,0xbef13e48,0x3f753f0e,0x3e953f55,0xbe953ec4,0xbf75bf6d,0x3ef13f6d,0xbf62bec4,
0xbf7fbf55,0x3dc9bf0e,0xbf46be48,0xbf22bf7b,0x3f353f80,0xbf350000,0x3f353f80,0xbf350000,0xbf350000,0xbf35bf80,0xbf350000,0xbf35bf80,
0xbf35bf80,0x3f350000,0xbf35bf80,0x3f350000,0x3f350000,0x3f353f80,0x3f350000,0x3f353f80,0xbf460000,0xbf22bf80,0xbf7fbf35,0x3dc9bf35,
0xbef1bf7b,0x3f623e48,0x3e95bf0e,0x3f753f55,0x3f753ec4,0x3e953f6d,0x3f623f6d,0xbef13ec4,0x3dc93f55,0xbf7fbf0e,0xbf223e48,0xbf46bf7b,
0xbf0ebf80,0x3f550000,0x3f550000,0x3f0e3f80,0x3f7b3ec4,0x3e483f6d,0x3e483f6d,0xbf7bbec4,0xbe483f35,0xbf7bbf35,0xbf7bbf35,0x3e48bf35,
0xbf55bf6d,0x3f0ebec4,0x3f0ebec4,0x3f553f6d,0x3f620000,0x3ef13f80,0xbe953f35,0xbf75bf35,0xbdc93f55,0xbf7fbf0e,0xbf22bf7b,0x3f46be48,
0xbf46bf6d,0x3f22bec4,0x3f7f3ec4,0x3dc93f6d,0x3f753e48,0x3e953f7b,0xbef13f0e,0xbf62bf55,0x3ec43f80,0xbf6d0000,0xbec4bf80,0x3f6d0000,
0xbf6dbf35,0x3ec4bf35,0x3f6d3f35,0xbec43f35,0x3f6d0000,0x3ec43f80,0xbf6d0000,0xbec4bf80,0xbec43f35,0xbf6dbf35,0x3ec4bf35,0x3f6d3f35,
0xbf750000,0xbe95bf80,0x3f623f35,0xbef13f35,0x3f22bf0e,0x3f463f55,0xbf7fbe48,0xbdc9bf7b,0xbdc93f6d,0xbf7fbec4,0x3f46bec4,0x3f223f6d,
0xbef1bf7b,0x3f62be48,0xbe953f55,0xbf75bf0e,0xbe48bf80,0x3f7b0000,0xbf7b0000,0xbe48bf80,0x3f0e3f6d,0xbf553ec4,0x3f55bec4,0x3f0e3f6d,
0xbf55bf35,0x3f0ebf35,0xbf0e3f35,0xbf55bf35,0x3f7b3ec4,0xbe483f6d,0x3e48bf6d,0x3f7b3ec4,0x3f7f0000,0x3dc93f80,0x3f22bf35,0x3f463f35,
0xbf753e48,0xbe95bf7b,0xbef13f55,0xbf62bf0e,0x3f62bec4,0x3ef13f6d,0x3e95bf6d,0x3f753ec4,0xbf463f0e,0xbf22bf55,0xbdc93f7b,0xbf7fbe48,
0x3f80,0xbf800000,0x3f80,0xbf800000,0xbf80,0x3f800000,0xbf80,0x3f800000,0x3f80,0xbf800000,0x3f80,0xbf800000,
0xbf80,0x3f800000,0xbf80,0x3f800000,0xbf7f0000,0x3dc9bf80,0xbf22bf35,0x3f46bf35,0x3f753e48,0xbe953f7b,0x3ef13f55,0xbf623f0e,
0xbf62bec4,0x3ef1bf6d,0xbe95bf6d,0x3f75bec4,0x3f463f0e,0xbf223f55,0x3dc93f7b,0xbf7f3e48,0x3e48bf80,0x3f7b0000,0x3f7b0000,0xbe483f80,
0xbf0e3f6d,0xbf55bec4,0xbf55bec4,0x3f0ebf6d,0x3f55bf35,0x3f0e3f35,0x3f0e3f35,0xbf553f35,0xbf7b3ec4,0xbe48bf6d,0xbe48bf6d,0x3f7bbec4,
0x3f750000,0xbe953f80,0xbf623f35,0xbef1bf35,0xbf22bf0e,0x3f46bf55,0x3f7fbe48,0xbdc93f7b,0x3dc93f6d,0xbf7f3ec4,0xbf46bec4,0x3f22bf6d,
0x3ef1bf7b,0x3f623e48,0x3e953f55,0xbf753f0e,0xbec43f80,0xbf6d0000,0x3ec4bf80,0x3f6d0000,0x3f6dbf35,0x3ec43f35,0xbf6d3f35,0xbec4bf35,
0xbf6d0000,0x3ec4bf80,0x3f6d0000,0xbec43f80,0x3ec43f35,0xbf6d3f35,0xbec4bf35,0x3f6dbf35,0xbf620000,0x3ef1bf80,0x3e953f35,0xbf753f35,
0x3dc93f55,0xbf7f3f0e,0x3f22bf7b,0x3f463e48,0x3f46bf6d,0x3f223ec4,0xbf7f3ec4,0x3dc9bf6d,0xbf753e48,0x3e95bf7b,0x3ef13f0e,0xbf623f55,
0x3f0ebf80,0x3f550000,0xbf550000,0x3f0ebf80,0xbf7b3ec4,0x3e48bf6d,0xbe483f6d,0xbf7b3ec4,0x3e483f35,0xbf7b3f35,0x3f7bbf35,0x3e483f35,
0x3f55bf6d,0x3f0e3ec4,0xbf0ebec4,0x3f55bf6d,0x3f460000,0xbf223f80,0x3f7fbf35,0x3dc93f35,0x3ef1bf7b,0x3f62be48,0xbe95bf0e,0x3f75bf55,
0xbf753ec4,0x3e95bf6d,0xbf623f6d,0xbef1bec4,0xbdc93f55,0xbf7f3f0e,0x3f223e48,0xbf463f7b,0xbf353f80,0xbf350000,0xbf353f80,0xbf350000,
0x3f350000,0xbf353f80,0x3f350000,0xbf353f80,0x3f35bf80,0x3f350000,0x3f35bf80,0x3f350000,0xbf350000,0x3f35bf80,0xbf350000,0x3f35bf80,
0xbf220000,0x3f46bf80,0x3dc9bf35,0x3f7fbf35,0xbf623f7b,0xbef1be48,0xbf753f0e,0x3e95bf55,0x3e953ec4,0xbf753f6d,0xbef13f6d,0xbf623ec4,
0x3f7fbf55,0x3dc93f0e,0x3f46be48,0xbf223f7b,0x3f55bf80,0x3f0e0000,0x3f0e0000,0xbf553f80,0xbe48bec4,0x3f7bbf6d,0x3f7bbf6d,0x3e483ec4,
0xbf7b3f35,0x3e48bf35,0x3e48bf35,0x3f7bbf35,0xbf0e3f6d,0xbf553ec4,0xbf553ec4,0x3f0ebf6d,0x3ef10000,0xbf623f80,0xbf753f35,0x3e95bf35,
0x3f7fbf55,0xbdc93f0e,0xbf463f7b,0xbf223e48,0x3f22bf6d,0x3f46bec4,0x3dc93ec4,0xbf7f3f6d,0xbe95be48,0x3f75bf7b,0x3f62bf0e,0xbef13f55,
0xbf6d3f80,0xbec40000,0x3f6dbf80,0x3ec40000,0xbec43f35,0xbf6d3f35,0x3ec4bf35,0x3f6dbf35,0x3ec40000,0xbf6d3f80,0xbec40000,0x3f6dbf80,
0x3f6dbf35,0xbec43f35,0xbf6d3f35,0x3ec4bf35,0xbe950000,0x3f75bf80,0xbef13f35,0xbf623f35,0xbf463f0e,0x3f22bf55,0x3dc93e48,0xbf7f3f7b,
0xbf7f3f6d,0x3dc9bec4,0x3f22bec4,0xbf463f6d,0xbf623f7b,0xbef13e48,0x3f75bf55,0xbe953f0e,0x3f7bbf80,0x3e480000,0xbe480000,0x3f7bbf80,
0x3f55bf6d,0x3f0ebec4,0xbf0e3ec4,0x3f55bf6d,0x3f0ebf35,0x3f55bf35,0xbf553f35,0x3f0ebf35,0x3e48bec4,0x3f7bbf6d,0xbf7b3f6d,0x3e48bec4,
0x3dc90000,0xbf7f3f80,0x3f46bf35,0xbf223f35,0x3e95be48,0xbf753f7b,0x3f62bf55,0xbef13f0e,0x3ef1bec4,0xbf623f6d,0x3f75bf6d,0xbe953ec4,
0x3f22bf0e,0xbf463f55,0x3f7fbf7b,0xbdc93e48,0x3f803f80,0xbf803f80,0x3f803f80,0xbf803f80,0x3f803f80,0xbf803f80,0x3f803f80,0xbf803f80,
0x3f803f80,0xbf803f80,0x3f803f80,0xbf803f80,0x3f803f80,0xbf803f80,0x3f803f80,0xbf803f80,0xbf7fbf80,0x3dc90000,0xbf22bf35,0x3f463f35,
0xbf75bf7b,0x3e953e48,0xbef1bf0e,0x3f623f55,0xbf62bf6d,0x3ef13ec4,0xbe95bec4,0x3f753f6d,0xbf46bf55,0x3f223f0e,0xbdc9be48,0x3f7f3f7b,
0x3f7b3f80,0xbe480000,0xbe480000,0xbf7bbf80,0x3f553f6d,0xbf0ebec4,0xbf0ebec4,0xbf55bf6d,0x3f0e3f35,0xbf55bf35,0xbf55bf35,0xbf0ebf35,
0x3e483ec4,0xbf7bbf6d,0xbf7bbf6d,0xbe48bec4,0xbf75bf80,0x3e950000,0x3f623f35,0x3ef13f35,0xbf22bf55,0x3f463f0e,0x3f7f3f7b,0xbdc93e48,
0xbdc9bec4,0x3f7f3f6d,0x3f463f6d,0xbf22bec4,0x3ef13e48,0x3f623f7b,0x3e953f0e,0xbf75bf55,0x3f6d3f80,0xbec40000,0xbf6dbf80,0x3ec40000,
0x3ec43f35,0xbf6dbf35,0xbec4bf35,0x3f6d3f35,0xbec40000,0xbf6dbf80,0x3ec40000,0x3f6d3f80,0xbf6dbf35,0xbec4bf35,0x3f6d3f35,0x3ec43f35,
0xbf62bf80,0x3ef10000,0x3e953f35,0xbf75bf35,0xbdc9bf0e,0x3f7f3f55,0xbf22be48,0xbf46bf7b,0x3f463ec4,0x3f223f6d,0xbf7fbf6d,0x3dc9bec4,
0x3f753f7b,0xbe953e48,0xbef1bf55,0x3f623f0e,0x3f553f80,0xbf0e0000,0x3f0e0000,0x3f553f80,0xbe483ec4,0xbf7bbf6d,0x3f7b3f6d,0xbe483ec4,
0xbf7bbf35,0xbe48bf35,0x3e483f35,0xbf7bbf35,0xbf0ebf6d,0x3f553ec4,0xbf55bec4,0xbf0ebf6d,0xbf46bf80,0x3f220000,0xbf7fbf35,0xbdc9bf35,
0x3ef1be48,0x3f623f7b,0xbe95bf55,0x3f753f0e,0x3f753f6d,0xbe953ec4,0x3f623ec4,0x3ef13f6d,0xbdc93f0e,0xbf7fbf55,0x3f223f7b,0xbf46be48,
0x3f353f80,0xbf350000,0x3f353f80,0xbf350000,0xbf350000,0xbf35bf80,0xbf350000,0xbf35bf80,0xbf35bf80,0x3f350000,0xbf35bf80,0x3f350000,
0x3f350000,0x3f353f80,0x3f350000,0x3f353f80,0xbf22bf80,0x3f460000,0x3dc9bf35,0x3f7f3f35,0x3f623e48,0x3ef13f7b,0x3f753f55,0xbe953f0e,
0x3e953f6d,0xbf75bec4,0xbef13ec4,0xbf62bf6d,0xbf7fbf0e,0xbdc9bf55,0xbf46bf7b,0x3f22be48,0x3f0e3f80,0xbf550000,0xbf550000,0xbf0ebf80,
0xbf7bbec4,0xbe48bf6d,0xbe48bf6d,0x3f7b3ec4,0x3e48bf35,0x3f7b3f35,0x3f7b3f35,0xbe483f35,0x3f553f6d,0xbf0e3ec4,0xbf0e3ec4,0xbf55bf6d,
0xbef1bf80,0x3f620000,0x3f753f35,0xbe953f35,0x3f7f3f0e,0xbdc93f55,0xbf463e48,0xbf22bf7b,0xbf223ec4,0xbf46bf6d,0xbdc9bf6d,0x3f7f3ec4,
0xbe95bf7b,0x3f753e48,0x3f623f55,0xbef13f0e,0x3ec43f80,0xbf6d0000,0xbec4bf80,0x3f6d0000,0xbf6dbf35,0x3ec4bf35,0x3f6d3f35,0xbec43f35,
0x3f6d0000,0x3ec43f80,0xbf6d0000,0xbec4bf80,0xbec43f35,0xbf6dbf35,0x3ec4bf35,0x3f6d3f35,0xbe95bf80,0x3f750000,0xbef13f35,0xbf62bf35,
0x3f463f55,0xbf223f0e,0xbdc9bf7b,0x3f7f3e48,0xbf7fbec4,0x3dc9bf6d,0x3f223f6d,0xbf463ec4,0x3f62be48,0x3ef13f7b,0xbf75bf0e,0x3e95bf55,
0x3e483f80,0xbf7b0000,0x3f7b0000,0x3e483f80,0xbf0ebf6d,0x3f55bec4,0xbf553ec4,0xbf0ebf6d,0x3f553f35,0xbf0e3f35,0x3f0ebf35,0x3f553f35,
0xbf7bbec4,0x3e48bf6d,0xbe483f6d,0xbf7bbec4,0xbdc9bf80,0x3f7f0000,0xbf46bf35,0x3f22bf35,0x3e953f7b,0xbf753e48,0x3f623f0e,0xbef13f55,
0xbef1bf6d,0x3f62bec4,0xbf75bec4,0x3e95bf6d,0x3f223f55,0xbf463f0e,0x3f7f3e48,0xbdc93f7b,0x3f80,0xbf800000,0x3f80,0xbf800000,
0xbf80,0x3f800000,0xbf80,0x3f800000,0x3f80,0xbf800000,0x3f80,0xbf800000,0xbf80,0x3f800000,0xbf80,0x3f800000,
0x3dc9bf80,0x3f7f0000,0x3f46bf35,0x3f223f35,0xbe953f7b,0xbf75be48,0xbf623f0e,0xbef1bf55,0x3ef1bf6d,0x3f623ec4,0x3f75bec4,0x3e953f6d,
0xbf223f55,0xbf46bf0e,0xbf7f3e48,0xbdc9bf7b,0xbe483f80,0xbf7b0000,0xbf7b0000,0x3e48bf80,0x3f0ebf6d,0x3f553ec4,0x3f553ec4,0xbf0e3f6d,
0xbf553f35,0xbf0ebf35,0xbf0ebf35,0x3f55bf35,0x3f7bbec4,0x3e483f6d,0x3e483f6d,0xbf7b3ec4,0x3e95bf80,0x3f750000,0x3ef13f35,0xbf623f35,
0xbf463f55,0xbf22bf0e,0x3dc9bf7b,0x3f7fbe48,0x3f7fbec4,0x3dc93f6d,0xbf223f6d,0xbf46bec4,0xbf62be48,0x3ef1bf7b,0x3f75bf0e,0x3e953f55,
0xbec43f80,0xbf6d0000,0x3ec4bf80,0x3f6d0000,0x3f6dbf35,0x3ec43f35,0xbf6d3f35,0xbec4bf35,0xbf6d0000,0x3ec4bf80,0x3f6d0000,0xbec43f80,
0x3ec43f35,0xbf6d3f35,0xbec4bf35,0x3f6dbf35,0x3ef1bf80,0x3f620000,0xbf753f35,0xbe95bf35,0xbf7f3f0e,0xbdc9bf55,0x3f463e48,0xbf223f7b,
0x3f223ec4,0xbf463f6d,0x3dc9bf6d,0x3f7fbec4,0x3e95bf7b,0x3f75be48,0xbf623f55,0xbef1bf0e,0xbf0e3f80,0xbf550000,0x3f550000,0xbf0e3f80,
0x3f7bbec4,0xbe483f6d,0x3e48bf6d,0x3f7bbec4,0xbe48bf35,0x3f7bbf35,0xbf7b3f35,0xbe48bf35,0xbf553f6d,0xbf0ebec4,0x3f0e3ec4,0xbf553f6d,
0x3f22bf80,0x3f460000,0xbdc9bf35,0x3f7fbf35,0xbf623e48,0x3ef1bf7b,0xbf753f55,0xbe95bf0e,0xbe953f6d,0xbf753ec4,0x3ef13ec4,0xbf623f6d,
0x3f7fbf0e,0xbdc93f55,0x3f46bf7b,0x3f223e48,0xbf353f80,0xbf350000,0xbf353f80,0xbf350000,0x3f350000,0xbf353f80,0x3f350000,0xbf353f80,
0x3f35bf80,0x3f350000,0x3f35bf80,0x3f350000,0xbf350000,0x3f35bf80,0xbf350000,0x3f35bf80,0x3f46bf80,0x3f220000,0x3f7fbf35,0xbdc93f35,
0xbef1be48,0x3f62bf7b,0x3e95bf55,0x3f75bf0e,0xbf753f6d,0xbe95bec4,0xbf623ec4,0x3ef1bf6d,0x3dc93f0e,0xbf7f3f55,0xbf223f7b,0xbf463e48,
0xbf553f80,0xbf0e0000,0xbf0e0000,0x3f55bf80,0x3e483ec4,0xbf7b3f6d,0xbf7b3f6d,0xbe48bec4,0x3f7bbf35,0xbe483f35,0xbe483f35,0xbf7b3f35,
0x3f0ebf6d,0x3f55bec4,0x3f55bec4,0xbf0e3f6d,0x3f62bf80,0x3ef10000,0xbe953f35,0xbf753f35,0x3dc9bf0e,0x3f7fbf55,0x3f22be48,0xbf463f7b,
0xbf463ec4,0x3f22bf6d,0x3f7fbf6d,0x3dc93ec4,0xbf753f7b,0xbe95be48,0x3ef1bf55,0x3f62bf0e,0xbf6d3f80,0xbec40000,0x3f6dbf80,0x3ec40000,
0xbec43f35,0xbf6d3f35,0x3ec4bf35,0x3f6dbf35,0x3ec40000,0xbf6d3f80,0xbec40000,0x3f6dbf80,0x3f6dbf35,0xbec43f35,0xbf6d3f35,0x3ec4bf35,
0x3f75bf80,0x3e950000,0xbf623f35,0x3ef1bf35,0x3f22bf55,0x3f46bf0e,0xbf7f3f7b,0xbdc9be48,0x3dc9bec4,0x3f7fbf6d,0xbf463f6d,0xbf223ec4,
0xbef13e48,0x3f62bf7b,0xbe953f0e,0xbf753f55,0xbf7b3f80,0xbe480000,0x3e480000,0xbf7b3f80,0xbf553f6d,0xbf0e3ec4,0x3f0ebec4,0xbf553f6d,
0xbf0e3f35,0xbf553f35,0x3f55bf35,0xbf0e3f35,0xbe483ec4,0xbf7b3f6d,0x3f7bbf6d,0xbe483ec4,0x3f7fbf80,0x3dc90000,0x3f22bf35,0x3f46bf35,
0x3f75bf7b,0x3e95be48,0x3ef1bf0e,0x3f62bf55,0x3f62bf6d,0x3ef1bec4,0x3e95bec4,0x3f75bf6d,0x3f46bf55,0x3f22bf0e,0x3dc9be48,0x3f7fbf7b,
0x3f803f80,0xbf803f80,0x3f803f80,0xbf803f80,0x3f803f80,0xbf803f80,0x3f803f80,0xbf803f80,0x3f803f80,0xbf803f80,0x3f803f80,0xbf803f80,
0x3f803f80,0xbf803f80,0x3f803f80,0xbf803f80,0x3dc90000,0x3f7f3f80,0x3f463f35,0x3f223f35,0x3e953e48,0x3f753f7b,0x3f623f55,0x3ef13f0e,
0x3ef13ec4,0x3f623f6d,0x3f753f6d,0x3e953ec4,0x3f223f0e,0x3f463f55,0x3f7f3f7b,0x3dc93e48,0xbf7bbf80,0x3e480000,0x3e480000,0x3f7b3f80,
0xbf55bf6d,0x3f0e3ec4,0x3f0e3ec4,0x3f553f6d,0xbf0ebf35,0x3f553f35,0x3f553f35,0x3f0e3f35,0xbe48bec4,0x3f7b3f6d,0x3f7b3f6d,0x3e483ec4,
0xbe950000,0xbf75bf80,0xbef1bf35,0x3f623f35,0xbf46bf0e,0xbf22bf55,0x3dc9be48,0x3f7f3f7b,0xbf7fbf6d,0xbdc9bec4,0x3f223ec4,0x3f463f6d,
0xbf62bf7b,0x3ef13e48,0x3f753f55,0x3e953f0e,0x3f6d3f80,0xbec40000,0xbf6dbf80,0x3ec40000,0x3ec43f35,0xbf6dbf35,0xbec4bf35,0x3f6d3f35,
0xbec40000,0xbf6dbf80,0x3ec40000,0x3f6d3f80,0xbf6dbf35,0xbec4bf35,0x3f6d3f35,0x3ec43f35,0x3ef10000,0x3f623f80,0xbf75bf35,0xbe95bf35,
0x3f7f3f55,0x3dc93f0e,0xbf46bf7b,0x3f223e48,0x3f223f6d,0xbf46bec4,0x3dc9bec4,0x3f7f3f6d,0xbe953e48,0xbf75bf7b,0x3f623f0e,0x3ef13f55,
0xbf55bf80,0x3f0e0000,0xbf0e0000,0xbf55bf80,0x3e48bec4,0x3f7b3f6d,0xbf7bbf6d,0x3e48bec4,0x3f7b3f35,0x3e483f35,0xbe48bf35,0x3f7b3f35,
0x3f0e3f6d,0xbf55bec4,0x3f553ec4,0x3f0e3f6d,0xbf220000,0xbf46bf80,0x3dc93f35,0xbf7fbf35,0xbf62bf7b,0x3ef1be48,0xbf75bf0e,0xbe95bf55,
0x3e95bec4,0x3f753f6d,0xbef1bf6d,0x3f623ec4,0x3f7f3f55,0xbdc93f0e,0x3f463e48,0x3f223f7b,0x3f353f80,0xbf350000,0x3f353f80,0xbf350000,
0xbf350000,0xbf35bf80,0xbf350000,0xbf35bf80,0xbf35bf80,0x3f350000,0xbf35bf80,0x3f350000,0x3f350000,0x3f353f80,0x3f350000,0x3f353f80,
0x3f460000,0x3f223f80,0x3f7f3f35,0xbdc93f35,0x3ef13f7b,0xbf62be48,0xbe953f0e,0xbf75bf55,0xbf75bec4,0xbe95bf6d,0xbf62bf6d,0x3ef1bec4,
0xbdc9bf55,0x3f7f3f0e,0x3f22be48,0x3f463f7b,0xbf0ebf80,0x3f550000,0x3f550000,0x3f0e3f80,0x3f7b3ec4,0x3e483f6d,0x3e483f6d,0xbf7bbec4,
0xbe483f35,0xbf7bbf35,0xbf7bbf35,0x3e48bf35,0xbf55bf6d,0x3f0ebec4,0x3f0ebec4,0x3f553f6d,0xbf620000,0xbef1bf80,0x3e95bf35,0x3f753f35,
0x3dc9bf55,0x3f7f3f0e,0x3f223f7b,0xbf463e48,0x3f463f6d,0xbf223ec4,0xbf7fbec4,0xbdc9bf6d,0xbf75be48,0xbe95bf7b,0x3ef1bf0e,0x3f623f55,
0x3ec43f80,0xbf6d0000,0xbec4bf80,0x3f6d0000,0xbf6dbf35,0x3ec4bf35,0x3f6d3f35,0xbec43f35,0x3f6d0000,0x3ec43f80,0xbf6d0000,0xbec4bf80,
0xbec43f35,0xbf6dbf35,0x3ec4bf35,0x3f6d3f35,0x3f750000,0x3e953f80,0xbf62bf35,0x3ef1bf35,0xbf223f0e,0xbf46bf55,0x3f7f3e48,0x3dc93f7b,
0x3dc9bf6d,0x3f7f3ec4,0xbf463ec4,0xbf22bf6d,0x3ef13f7b,0xbf623e48,0x3e95bf55,0x3f753f0e,0xbe48bf80,0x3f7b0000,0xbf7b0000,0xbe48bf80,
0x3f0e3f6d,0xbf553ec4,0x3f55bec4,0x3f0e3f6d,0xbf55bf35,0x3f0ebf35,0xbf0e3f35,0xbf55bf35,0x3f7b3ec4,0xbe483f6d,0x3e48bf6d,0x3f7b3ec4,
0xbf7f0000,0xbdc9bf80,0xbf223f35,0xbf46bf35,0x3f75be48,0x3e953f7b,0x3ef1bf55,0x3f623f0e,0xbf623ec4,0xbef1bf6d,0xbe953f6d,0xbf75bec4,
0x3f46bf0e,0x3f223f55,0x3dc9bf7b,0x3f7f3e48,0x3f80,0xbf800000,0x3f80,0xbf800000,0xbf80,0x3f800000,0xbf80,0x3f800000,
0x3f80,0xbf800000,0x3f80,0xbf800000,0xbf80,0x3f800000,0xbf80,0x3f800000,0x3f7f0000,0xbdc93f80,0x3f223f35,0xbf463f35,
0xbf75be48,0x3e95bf7b,0xbef1bf55,0x3f62bf0e,0x3f623ec4,0xbef13f6d,0x3e953f6d,0xbf753ec4,0xbf46bf0e,0x3f22bf55,0xbdc9bf7b,0x3f7fbe48,
0x3e48bf80,0x3f7b0000,0x3f7b0000,0xbe483f80,0xbf0e3f6d,0xbf55bec4,0xbf55bec4,0x3f0ebf6d,0x3f55bf35,0x3f0e3f35,0x3f0e3f35,0xbf553f35,
0xbf7b3ec4,0xbe48bf6d,0xbe48bf6d,0x3f7bbec4,0xbf750000,0x3e95bf80,0x3f62bf35,0x3ef13f35,0x3f223f0e,0xbf463f55,0xbf7f3e48,0x3dc9bf7b,
0xbdc9bf6d,0x3f7fbec4,0x3f463ec4,0xbf223f6d,0xbef13f7b,0xbf62be48,0xbe95bf55,0x3f75bf0e,0xbec43f80,0xbf6d0000,0x3ec4bf80,0x3f6d0000,
0x3f6dbf35,0x3ec43f35,0xbf6d3f35,0xbec4bf35,0xbf6d0000,0x3ec4bf80,0x3f6d0000,0xbec43f80,0x3ec43f35,0xbf6d3f35,0xbec4bf35,0x3f6dbf35,
0x3f620000,0xbef13f80,0xbe95bf35,0x3f75bf35,0xbdc9bf55,0x3f7fbf0e,0xbf223f7b,0xbf46be48,0xbf463f6d,0xbf22bec4,0x3f7fbec4,0xbdc93f6d,
0x3f75be48,0xbe953f7b,0xbef1bf0e,0x3f62bf55,0x3f0ebf80,0x3f550000,0xbf550000,0x3f0ebf80,0xbf7b3ec4,0x3e48bf6d,0xbe483f6d,0xbf7b3ec4,
0x3e483f35,0xbf7b3f35,0x3f7bbf35,0x3e483f35,0x3f55bf6d,0x3f0e3ec4,0xbf0ebec4,0x3f55bf6d,0xbf460000,0x3f22bf80,0xbf7f3f35,0xbdc9bf35,
0xbef13f7b,0xbf623e48,0x3e953f0e,0xbf753f55,0x3f75bec4,0xbe953f6d,0x3f62bf6d,0x3ef13ec4,0x3dc9bf55,0x3f7fbf0e,0xbf22be48,0x3f46bf7b,
0xbf353f80,0xbf350000,0xbf353f80,0xbf350000,0x3f350000,0xbf353f80,0x3f350000,0xbf353f80,0x3f35bf80,0x3f350000,0x3f35bf80,0x3f350000,
0xbf350000,0x3f35bf80,0xbf350000,0x3f35bf80,0x3f220000,0xbf463f80,0xbdc93f35,0xbf7f3f35,0x3f62bf7b,0x3ef13e48,0x3f75bf0e,0xbe953f55,
0xbe95bec4,0x3f75bf6d,0x3ef1bf6d,0x3f62bec4,0xbf7f3f55,0xbdc9bf0e,0xbf463e48,0x3f22bf7b,0x3f55bf80,0x3f0e0000,0x3f0e0000,0xbf553f80,
0xbe48bec4,0x3f7bbf6d,0x3f7bbf6d,0x3e483ec4,0xbf7b3f35,0x3e48bf35,0x3e48bf35,0x3f7bbf35,0xbf0e3f6d,0xbf553ec4,0xbf553ec4,0x3f0ebf6d,
0xbef10000,0x3f62bf80,0x3f75bf35,0xbe953f35,0xbf7f3f55,0x3dc9bf0e,0x3f46bf7b,0x3f22be48,0xbf223f6d,0xbf463ec4,0xbdc9bec4,0x3f7fbf6d,
0x3e953e48,0xbf753f7b,0xbf623f0e,0x3ef1bf55,0xbf6d3f80,0xbec40000,0x3f6dbf80,0x3ec40000,0xbec43f35,0xbf6d3f35,0x3ec4bf35,0x3f6dbf35,
0x3ec40000,0xbf6d3f80,0xbec40000,0x3f6dbf80,0x3f6dbf35,0xbec43f35,0xbf6d3f35,0x3ec4bf35,0x3e950000,0xbf753f80,0x3ef1bf35,0x3f62bf35,
0x3f46bf0e,0xbf223f55,0xbdc9be48,0x3f7fbf7b,0x3f7fbf6d,0xbdc93ec4,0xbf223ec4,0x3f46bf6d,0x3f62bf7b,0x3ef1be48,0xbf753f55,0x3e95bf0e,
0x3f7bbf80,0x3e480000,0xbe480000,0x3f7bbf80,0x3f55bf6d,0x3f0ebec4,0xbf0e3ec4,0x3f55bf6d,0x3f0ebf35,0x3f55bf35,0xbf553f35,0x3f0ebf35,
0x3e48bec4,0x3f7bbf6d,0xbf7b3f6d,0x3e48bec4,0xbdc90000,0x3f7fbf80,0xbf463f35,0x3f22bf35,0xbe953e48,0x3f75bf7b,0xbf623f55,0x3ef1bf0e,
0xbef13ec4,0x3f62bf6d,0xbf753f6d,0x3e95bec4,0xbf223f0e,0x3f46bf55,0xbf7f3f7b,0x3dc9be48,0x40003f80,0x3fb53f80,0x3f80,0xbfb53f80,
0x40004000,0xbfb50000,0x0,0xbfb5c000,0x40004000,0xbfb5c000,0x0,0x3fb50000,0x40004000,0x3fb50000,0x0,0x3fb54000,
0x3fff3f80,0x3fa23f80,0xbe49bf80,0xbfc6bf80,0x3ff53ffb,0xbfe2bec8,0xbf15bec8,0xbf71bffb,0x3fe23fed,0xbf15bfed,0xbf71bf44,0x3ff53f44,
0x3fc63fd5,0x3fff3f8e,0xbfa2bf8e,0x3e493fd5,0x3ffb3f80,0x3f8e3f80,0xbec83f80,0xbfd53f80,0x3fd53fed,0xbffbbf44,0xbf8ebf44,0xbec8bfed,
0x3f8e3fb5,0x3ec8bfb5,0xbfd5bfb5,0x3ffb3fb5,0x3ec83f44,0x3fd53fed,0xbffbbfed,0xbf8e3f44,0x3ff53f80,0x3f713f80,0xbf15bf80,0xbfe2bf80,
0x3fa23fd5,0xbfffbf8e,0xbfc6bf8e,0x3e49bfd5,0x3e493f44,0x3fa2bf44,0xbfffbfed,0x3fc63fed,0xbf71bec8,0x3f153ffb,0xbfe2bffb,0xbff5bec8,
0x3fed3f80,0x3f443f80,0xbf443f80,0xbfed3f80,0x3f443fb5,0xbfedbfb5,0xbfedbfb5,0x3f44bfb5,0xbf440000,0x3fed0000,0xbfedc000,0x3f444000,
0xbfedbfb5,0xbf443fb5,0xbf44bfb5,0xbfedbfb5,0x3fe23f80,0x3f153f80,0xbf71bf80,0xbff5bf80,0x3e493f8e,0xbfc6bfd5,0xbfffbfd5,0x3fa2bf8e,
0xbfc6bf44,0x3fff3f44,0xbfa2bfed,0xbe493fed,0xbff5bffb,0xbfe23ec8,0x3f15bec8,0xbf71bffb,0x3fd53f80,0x3ec83f80,0xbf8e3f80,0xbffb3f80,
0xbec83f44,0xbf8ebfed,0xbffbbfed,0x3fd5bf44,0xbffbbfb5,0x3fd53fb5,0xbec8bfb5,0xbf8e3fb5,0xbf8ebfed,0xbffbbf44,0x3fd53f44,0x3ec8bfed,
0x3fc63f80,0x3e493f80,0xbfa2bf80,0xbfffbf80,0xbf713ec8,0xbf15bffb,0xbfe2bffb,0x3ff5bec8,0xbff5bfed,0x3f713fed,0x3f15bf44,0xbfe23f44,
0x3e49bf8e,0xbfa2bfd5,0x3fff3fd5,0x3fc6bf8e,0x3f80,0xbfb53f80,0xc0003f80,0xbfb53f80,0xc000,0x3fb50000,0x40000000,0xbfb54000,
0x4000,0x3fb5c000,0xc0000000,0x3fb50000,0xc000,0xbfb50000,0x40000000,0x3fb5c000,0xbe493f80,0xbfc63f80,0xbfffbf80,0xbfa2bf80,
0x3f15bffb,0x3f713ec8,0x3ff53ec8,0xbfe23ffb,0xbf713fed,0x3ff5bfed,0xbfe2bf44,0x3f153f44,0x3fa2bfd5,0xbe49bf8e,0x3fc63f8e,0x3fffbfd5,
0xbec83f80,0xbfd53f80,0xbffb3f80,0xbf8e3f80,0x3f8ebfed,0x3ec83f44,0x3fd53f44,0xbffb3fed,0xbfd53fb5,0x3ffbbfb5,0xbf8ebfb5,0xbec83fb5,
0x3ffbbf44,0x3f8ebfed,0x3ec83fed,0x3fd5bf44,0xbf153f80,0xbfe23f80,0xbff5bf80,0xbf71bf80,0x3fc6bfd5,0xbe493f8e,0x3fa23f8e,0xbfff3fd5,
0xbfff3f44,0x3fc6bf44,0xbe49bfed,0xbfa23fed,0x3fe23ec8,0x3ff5bffb,0xbf713ffb,0x3f153ec8,0xbf443f80,0xbfed3f80,0xbfed3f80,0xbf443f80,
0x3fedbfb5,0xbf443fb5,0x3f443fb5,0xbfed3fb5,0xbfed0000,0x3f440000,0x3f44c000,0xbfed4000,0x3f443fb5,0x3fedbfb5,0xbfed3fb5,0xbf443fb5,
0xbf713f80,0xbff53f80,0xbfe2bf80,0xbf15bf80,0x3fffbf8e,0xbfa23fd5,0x3e493fd5,0xbfc63f8e,0xbfa2bf44,0xbe493f44,0x3fc6bfed,0xbfff3fed,
0xbf153ffb,0x3f71bec8,0xbff53ec8,0xbfe23ffb,0xbf8e3f80,0xbffb3f80,0xbfd53f80,0xbec83f80,0x3ffbbf44,0xbfd53fed,0xbec83fed,0xbf8e3f44,
0xbec8bfb5,0xbf8e3fb5,0x3ffbbfb5,0xbfd53fb5,0xbfd53fed,0xbec83f44,0xbf8ebf44,0xbffb3fed,0xbfa23f80,0xbfff3f80,0xbfc6bf80,0xbe49bf80,
0x3fe2bec8,0xbff53ffb,0xbf713ffb,0xbf153ec8,0x3f15bfed,0xbfe23fed,0x3ff5bf44,0xbf713f44,0xbfff3f8e,0xbfc63fd5,0x3e49bfd5,0xbfa23f8e,
0xc0003f80,0xbfb53f80,0x3f80,0x3fb53f80,0xc0004000,0x3fb50000,0x0,0x3fb5c000,0xc0004000,0x3fb5c000,0x0,0xbfb50000,
0xc0004000,0xbfb50000,0x0,0xbfb54000,0xbfff3f80,0xbfa23f80,0x3e49bf80,0x3fc6bf80,0xbff53ffb,0x3fe2bec8,0x3f15bec8,0x3f71bffb,
0xbfe23fed,0x3f15bfed,0x3f71bf44,0xbff53f44,0xbfc63fd5,0xbfff3f8e,0x3fa2bf8e,0xbe493fd5,0xbffb3f80,0xbf8e3f80,0x3ec83f80,0x3fd53f80,
0xbfd53fed,0x3ffbbf44,0x3f8ebf44,0x3ec8bfed,0xbf8e3fb5,0xbec8bfb5,0x3fd5bfb5,0xbffb3fb5,0xbec83f44,0xbfd53fed,0x3ffbbfed,0x3f8e3f44,
0xbff53f80,0xbf713f80,0x3f15bf80,0x3fe2bf80,0xbfa23fd5,0x3fffbf8e,0x3fc6bf8e,0xbe49bfd5,0xbe493f44,0xbfa2bf44,0x3fffbfed,0xbfc63fed,
0x3f71bec8,0xbf153ffb,0x3fe2bffb,0x3ff5bec8,0xbfed3f80,0xbf443f80,0x3f443f80,0x3fed3f80,0xbf443fb5,0x3fedbfb5,0x3fedbfb5,0xbf44bfb5,
0x3f440000,0xbfed0000,0x3fedc000,0xbf444000,0x3fedbfb5,0x3f443fb5,0x3f44bfb5,0x3fedbfb5,0xbfe23f80,0xbf153f80,0x3f71bf80,0x3ff5bf80,
0xbe493f8e,0x3fc6bfd5,0x3fffbfd5,0xbfa2bf8e,0x3fc6bf44,0xbfff3f44,0x3fa2bfed,0x3e493fed,0x3ff5bffb,0x3fe23ec8,0xbf15bec8,0x3f71bffb,
0xbfd53f80,0xbec83f80,0x3f8e3f80,0x3ffb3f80,0x3ec83f44,0x3f8ebfed,0x3ffbbfed,0xbfd5bf44,0x3ffbbfb5,0xbfd53fb5,0x3ec8bfb5,0x3f8e3fb5,
0x3f8ebfed,0x3ffbbf44,0xbfd53f44,0xbec8bfed,0xbfc63f80,0xbe493f80,0x3fa2bf80,0x3fffbf80,0x3f713ec8,0x3f15bffb,0x3fe2bffb,0xbff5bec8,
0x3ff5bfed,0xbf713fed,0xbf15bf44,0x3fe23f44,0xbe49bf8e,0x3fa2bfd5,0xbfff3fd5,0xbfc6bf8e,0x3f80,0x3fb53f80,0x40003f80,0x3fb53f80,
0xc000,0xbfb50000,0xc0000000,0x3fb54000,0x4000,0xbfb5c000,0x40000000,0xbfb50000,0xc000,0x3fb50000,0xc0000000,0xbfb5c000,
0x3e493f80,0x3fc63f80,0x3fffbf80,0x3fa2bf80,0xbf15bffb,0xbf713ec8,0xbff53ec8,0x3fe23ffb,0x3f713fed,0xbff5bfed,0x3fe2bf44,0xbf153f44,
0xbfa2bfd5,0x3e49bf8e,0xbfc63f8e,0xbfffbfd5,0x3ec83f80,0x3fd53f80,0x3ffb3f80,0x3f8e3f80,0xbf8ebfed,0xbec83f44,0xbfd53f44,0x3ffb3fed,
0x3fd53fb5,0xbffbbfb5,0x3f8ebfb5,0x3ec83fb5,0xbffbbf44,0xbf8ebfed,0xbec83fed,0xbfd5bf44,0x3f153f80,0x3fe23f80,0x3ff5bf80,0x3f71bf80,
0xbfc6bfd5,0x3e493f8e,0xbfa23f8e,0x3fff3fd5,0x3fff3f44,0xbfc6bf44,0x3e49bfed,0x3fa23fed,0xbfe23ec8,0xbff5bffb,0x3f713ffb,0xbf153ec8,
0x3f443f80,0x3fed3f80,0x3fed3f80,0x3f443f80,0xbfedbfb5,0x3f443fb5,0xbf443fb5,0x3fed3fb5,0x3fed0000,0xbf440000,0xbf44c000,0x3fed4000,
0xbf443fb5,0xbfedbfb5,0x3fed3fb5,0x3f443fb5,0x3f713f80,0x3ff53f80,0x3fe2bf80,0x3f15bf80,0xbfffbf8e,0x3fa23fd5,0xbe493fd5,0x3fc63f8e,
0x3fa2bf44,0x3e493f44,0xbfc6bfed,0x3fff3fed,0x3f153ffb,0xbf71bec8,0x3ff53ec8,0x3fe23ffb,0x3f8e3f80,0x3ffb3f80,0x3fd53f80,0x3ec83f80,
0xbffbbf44,0x3fd53fed,0x3ec83fed,0x3f8e3f44,0x3ec8bfb5,0x3f8e3fb5,0xbffbbfb5,0x3fd53fb5,0x3fd53fed,0x3ec83f44,0x3f8ebf44,0x3ffb3fed,
0x3fa23f80,0x3fff3f80,0x3fc6bf80,0x3e49bf80,0xbfe2bec8,0x3ff53ffb,0x3f713ffb,0x3f153ec8,0xbf15bfed,0x3fe23fed,0xbff5bf44,0x3f713f44,
0x3fff3f8e,0x3fc63fd5,0xbe49bfd5,0x3fa23f8e,0x40004000,0x3fb54000,0x0,0xbfb50000,0x40004000,0xbfb50000,0x0,0xbfb5c000,
0x40004000,0xbfb5c000,0x0,0x3fb50000,0x40004000,0x3fb50000,0x0,0x3fb54000,0x3fa23fb5,0xbe493fb5,0xbfc6bfb5,0xbfffbfb5,
0x3f713f8e,0xbff5bfd5,0xbfe2bfd5,0x3f15bf8e,0x3f153f44,0x3f71bf44,0xbff5bfed,0x3fe23fed,0x3e493ec8,0x3fc63ffb,0xbfffbffb,0xbfa23ec8,
0xbec80000,0xbfd50000,0xbffbc000,0xbf8ec000,0xbf8ebf44,0xbec8bfed,0xbfd5bfed,0x3ffb3f44,0xbfd5bfb5,0x3ffb3fb5,0xbf8ebfb5,0xbec83fb5,
0xbffbbfed,0xbf8e3f44,0xbec8bf44,0xbfd5bfed,0xbfe2bfb5,0xbff5bfb5,0xbf71bfb5,0x3f15bfb5,0xbfffbffb,0x3fc6bec8,0x3e49bec8,0x3fa23ffb,
0xbfc6bfed,0x3e493fed,0x3fa23f44,0xbfffbf44,0xbf15bf8e,0xbfe2bfd5,0x3ff53fd5,0x3f71bf8e,0xbfedc000,0xbf44c000,0x3f440000,0x3fed0000,
0xbf44bfb5,0x3fed3fb5,0x3fed3fb5,0xbf443fb5,0x3f440000,0xbfed0000,0x3fed4000,0xbf44c000,0x3fed3fb5,0x3f44bfb5,0x3f443fb5,0x3fed3fb5,
0xbf15bfb5,0x3f71bfb5,0x3ff53fb5,0x3fe23fb5,0x3fa23ec8,0x3e493ffb,0x3fc63ffb,0xbfffbec8,0x3fff3fed,0xbfa2bfed,0xbe493f44,0x3fc6bf44,
0x3f713fd5,0x3ff53f8e,0xbfe2bf8e,0xbf153fd5,0x3f8e0000,0x3ffb0000,0x3fd54000,0x3ec84000,0x3ffb3fed,0xbfd53f44,0xbec83f44,0xbf8ebfed,
0x3ec83fb5,0x3f8ebfb5,0xbffbbfb5,0x3fd53fb5,0xbfd5bf44,0xbec83fed,0xbf8ebfed,0xbffbbf44,0x3fff3fb5,0x3fc63fb5,0x3e493fb5,0xbfa23fb5,
0x3f153fd5,0xbfe2bf8e,0xbff5bf8e,0x3f71bfd5,0xbfe2bf44,0x3ff53f44,0xbf71bfed,0xbf153fed,0xbfa2bffb,0xbfffbec8,0x3fc63ec8,0x3e49bffb,
0x4000,0xbfb54000,0xc0000000,0xbfb50000,0xc000,0x3fb50000,0x40000000,0xbfb54000,0x4000,0x3fb5c000,0xc0000000,0x3fb50000,
0xc000,0xbfb50000,0x40000000,0x3fb5c000,0xbfc63fb5,0xbfff3fb5,0xbfa2bfb5,0x3e49bfb5,0x3fe2bf8e,0xbf153fd5,0x3f713fd5,0xbff53f8e,
0xbff53f44,0x3fe2bf44,0xbf15bfed,0xbf713fed,0x3fffbec8,0x3fa2bffb,0x3e493ffb,0x3fc6bec8,0xbffb0000,0xbf8e0000,0x3ec8c000,0x3fd5c000,
0x3fd53f44,0xbffb3fed,0xbf8e3fed,0xbec8bf44,0xbf8ebfb5,0xbec83fb5,0x3fd5bfb5,0xbffb3fb5,0x3ec83fed,0x3fd5bf44,0xbffb3f44,0xbf8e3fed,
0xbf71bfb5,0x3f15bfb5,0x3fe2bfb5,0x3ff5bfb5,0xbe493ffb,0xbfa23ec8,0xbfff3ec8,0x3fc6bffb,0x3fa2bfed,0xbfff3fed,0x3fc63f44,0xbe49bf44,
0xbff53f8e,0xbf713fd5,0xbf15bfd5,0xbfe23f8e,0x3f44c000,0x3fedc000,0x3fed0000,0x3f440000,0xbfed3fb5,0x3f44bfb5,0xbf44bfb5,0x3fedbfb5,
0x3fed0000,0xbf440000,0xbf444000,0x3fedc000,0xbf44bfb5,0xbfed3fb5,0x3fedbfb5,0x3f44bfb5,0x3ff5bfb5,0x3fe2bfb5,0x3f153fb5,0xbf713fb5,
0xbfc6bec8,0x3fffbffb,0x3fa2bffb,0x3e493ec8,0xbe493fed,0x3fc6bfed,0xbfff3f44,0x3fa2bf44,0x3fe2bfd5,0x3f15bf8e,0x3f713f8e,0x3ff5bfd5,
0x3fd50000,0x3ec80000,0xbf8e4000,0xbffb4000,0x3ec8bfed,0x3f8ebf44,0x3ffbbf44,0xbfd53fed,0xbffb3fb5,0x3fd5bfb5,0xbec8bfb5,0xbf8e3fb5,
0x3f8e3f44,0x3ffbbfed,0xbfd53fed,0xbec83f44,0x3e493fb5,0xbfa23fb5,0xbfff3fb5,0xbfc63fb5,0x3ff5bfd5,0xbf713f8e,0x3f153f8e,0xbfe23fd5,
0xbf71bf44,0xbf153f44,0x3fe2bfed,0xbff53fed,0xbfc63ffb,0xbe493ec8,0xbfa2bec8,0xbfff3ffb,0xc0004000,0xbfb54000,0x0,0x3fb50000,
0xc0004000,0x3fb50000,0x0,0x3fb5c000,0xc0004000,0x3fb5c000,0x0,0xbfb50000,0xc0004000,0xbfb50000,0x0,0xbfb54000,
0xbfa23fb5,0x3e493fb5,0x3fc6bfb5,0x3fffbfb5,0xbf713f8e,0x3ff5bfd5,0x3fe2bfd5,0xbf15bf8e,0xbf153f44,0xbf71bf44,0x3ff5bfed,0xbfe23fed,
0xbe493ec8,0xbfc63ffb,0x3fffbffb,0x3fa23ec8,0x3ec80000,0x3fd50000,0x3ffbc000,0x3f8ec000,0x3f8ebf44,0x3ec8bfed,0x3fd5bfed,0xbffb3f44,
0x3fd5bfb5,0xbffb3fb5,0x3f8ebfb5,0x3ec83fb5,0x3ffbbfed,0x3f8e3f44,0x3ec8bf44,0x3fd5bfed,0x3fe2bfb5,0x3ff5bfb5,0x3f71bfb5,0xbf15bfb5,
0x3fffbffb,0xbfc6bec8,0xbe49bec8,0xbfa23ffb,0x3fc6bfed,0xbe493fed,0xbfa23f44,0x3fffbf44,0x3f15bf8e,0x3fe2bfd5,0xbff53fd5,0xbf71bf8e,
0x3fedc000,0x3f44c000,0xbf440000,0xbfed0000,0x3f44bfb5,0xbfed3fb5,0xbfed3fb5,0x3f443fb5,0xbf440000,0x3fed0000,0xbfed4000,0x3f44c000,
0xbfed3fb5,0xbf44bfb5,0xbf443fb5,0xbfed3fb5,0x3f15bfb5,0xbf71bfb5,0xbff53fb5,0xbfe23fb5,0xbfa23ec8,0xbe493ffb,0xbfc63ffb,0x3fffbec8,
0xbfff3fed,0x3fa2bfed,0x3e493f44,0xbfc6bf44,0xbf713fd5,0xbff53f8e,0x3fe2bf8e,0x3f153fd5,0xbf8e0000,0xbffb0000,0xbfd54000,0xbec84000,
0xbffb3fed,0x3fd53f44,0x3ec83f44,0x3f8ebfed,0xbec83fb5,0xbf8ebfb5,0x3ffbbfb5,0xbfd53fb5,0x3fd5bf44,0x3ec83fed,0x3f8ebfed,0x3ffbbf44,
0xbfff3fb5,0xbfc63fb5,0xbe493fb5,0x3fa23fb5,0xbf153fd5,0x3fe2bf8e,0x3ff5bf8e,0xbf71bfd5,0x3fe2bf44,0xbff53f44,0x3f71bfed,0x3f153fed,
0x3fa2bffb,0x3fffbec8,0xbfc63ec8,0xbe49bffb,0x4000,0x3fb54000,0x40000000,0x3fb50000,0xc000,0xbfb50000,0xc0000000,0x3fb54000,
0x4000,0xbfb5c000,0x40000000,0xbfb50000,0xc000,0x3fb50000,0xc0000000,0xbfb5c000,0x3fc63fb5,0x3fff3fb5,0x3fa2bfb5,0xbe49bfb5,
0xbfe2bf8e,0x3f153fd5,0xbf713fd5,0x3ff53f8e,0x3ff53f44,0xbfe2bf44,0x3f15bfed,0x3f713fed,0xbfffbec8,0xbfa2bffb,0xbe493ffb,0xbfc6bec8,
0x3ffb0000,0x3f8e0000,0xbec8c000,0xbfd5c000,0xbfd53f44,0x3ffb3fed,0x3f8e3fed,0x3ec8bf44,0x3f8ebfb5,0x3ec83fb5,0xbfd5bfb5,0x3ffb3fb5,
0xbec83fed,0xbfd5bf44,0x3ffb3f44,0x3f8e3fed,0x3f71bfb5,0xbf15bfb5,0xbfe2bfb5,0xbff5bfb5,0x3e493ffb,0x3fa23ec8,0x3fff3ec8,0xbfc6bffb,
0xbfa2bfed,0x3fff3fed,0xbfc63f44,0x3e49bf44,0x3ff53f8e,0x3f713fd5,0x3f15bfd5,0x3fe23f8e,0xbf44c000,0xbfedc000,0xbfed0000,0xbf440000,
0x3fed3fb5,0xbf44bfb5,0x3f44bfb5,0xbfedbfb5,0xbfed0000,0x3f440000,0x3f444000,0xbfedc000,0x3f44bfb5,0x3fed3fb5,0xbfedbfb5,0xbf44bfb5,
0xbff5bfb5,0xbfe2bfb5,0xbf153fb5,0x3f713fb5,0x3fc6bec8,0xbfffbffb,0xbfa2bffb,0xbe493ec8,0x3e493fed,0xbfc6bfed,0x3fff3f44,0xbfa2bf44,
0xbfe2bfd5,0xbf15bf8e,0xbf713f8e,0xbff5bfd5,0xbfd50000,0xbec80000,0x3f8e4000,0x3ffb4000,0xbec8bfed,0xbf8ebf44,0xbffbbf44,0x3fd53fed,
0x3ffb3fb5,0xbfd5bfb5,0x3ec8bfb5,0x3f8e3fb5,0xbf8e3f44,0xbffbbfed,0x3fd53fed,0x3ec83f44,0xbe493fb5,0x3fa23fb5,0x3fff3fb5,0x3fc63fb5,
0xbff5bfd5,0x3f713f8e,0xbf153f8e,0x3fe23fd5,0x3f71bf44,0x3f153f44,0xbfe2bfed,0x3ff53fed,0x3fc63ffb,0x3e493ec8,0x3fa2bec8,0x3fff3ffb,
0x40004000,0x3fb54000,0x0,0xbfb50000,0x40004000,0xbfb50000,0x0,0xbfb5c000,0x40004000,0xbfb5c000,0x0,0x3fb50000,
0x40004000,0x3fb50000,0x0,0x3fb54000,0xbe490000,0xbfc60000,0xbfffc000,0xbfa2c000,0xbf15bec8,0xbf71bffb,0xbff5bffb,0x3fe23ec8,
0xbf71bf44,0x3ff53f44,0xbfe2bfed,0x3f153fed,0xbfa2bf8e,0x3e493fd5,0xbfc6bfd5,0xbfffbf8e,0xbffbc000,0xbf8ec000,0x3ec80000,0x3fd50000,
0xbfd5bfed,0x3ffb3f44,0x3f8e3f44,0x3ec83fed,0xbf8ebfb5,0xbec83fb5,0x3fd53fb5,0xbffbbfb5,0xbec8bf44,0xbfd5bfed,0x3ffb3fed,0x3f8ebf44,
0x3f150000,0x3fe20000,0x3ff54000,0x3f714000,0x3fc63f8e,0xbe493fd5,0x3fa23fd5,0xbfffbf8e,0x3fff3fed,0xbfc6bfed,0x3e493f44,0x3fa2bf44,
0x3fe23ffb,0x3ff53ec8,0xbf71bec8,0x3f153ffb,0x3fed4000,0x3f444000,0xbf440000,0xbfed0000,0x3f443fb5,0xbfedbfb5,0xbfedbfb5,0x3f44bfb5,
0xbf440000,0x3fed0000,0xbfedc000,0x3f444000,0xbfedbfb5,0xbf443fb5,0xbf44bfb5,0xbfedbfb5,0xbf710000,0xbff50000,0xbfe2c000,0xbf15c000,
0xbfffbfd5,0x3fa2bf8e,0xbe49bf8e,0x3fc63fd5,0xbfa2bfed,0xbe493fed,0x3fc63f44,0xbfffbf44,0x3f15bec8,0xbf71bffb,0x3ff53ffb,0x3fe2bec8,
0xbfd5c000,0xbec8c000,0x3f8e0000,0x3ffb0000,0x3ec8bf44,0x3f8e3fed,0x3ffb3fed,0xbfd53f44,0x3ffb3fb5,0xbfd5bfb5,0x3ec83fb5,0x3f8ebfb5,
0x3f8e3fed,0x3ffb3f44,0xbfd5bf44,0xbec83fed,0x3fa20000,0x3fff0000,0x3fc64000,0x3e494000,0x3fe23ffb,0xbff53ec8,0xbf713ec8,0xbf15bffb,
0xbf153f44,0x3fe2bf44,0xbff5bfed,0x3f713fed,0xbfffbfd5,0xbfc63f8e,0x3e49bf8e,0xbfa2bfd5,0x4000,0xbfb54000,0xc0000000,0xbfb50000,
0xc000,0x3fb50000,0x40000000,0xbfb54000,0x4000,0x3fb5c000,0xc0000000,0x3fb50000,0xc000,0xbfb50000,0x40000000,0x3fb5c000,
0xbfff0000,0xbfa20000,0x3e49c000,0x3fc6c000,0x3ff53ec8,0xbfe23ffb,0xbf153ffb,0xbf71bec8,0xbfe2bf44,0x3f153f44,0x3f71bfed,0xbff53fed,
0x3fc63f8e,0x3fffbfd5,0xbfa23fd5,0x3e493f8e,0x3ec8c000,0x3fd5c000,0x3ffb0000,0x3f8e0000,0xbf8e3fed,0xbec8bf44,0xbfd5bf44,0x3ffbbfed,
0x3fd5bfb5,0xbffb3fb5,0x3f8e3fb5,0x3ec8bfb5,0xbffb3f44,0xbf8e3fed,0xbec8bfed,0xbfd53f44,0x3ff50000,0x3f710000,0xbf154000,0xbfe24000,
0xbfa2bf8e,0x3fffbfd5,0x3fc6bfd5,0xbe493f8e,0x3e493fed,0x3fa2bfed,0xbfff3f44,0x3fc6bf44,0x3f71bffb,0xbf15bec8,0x3fe23ec8,0x3ff5bffb,
0xbf444000,0xbfed4000,0xbfed0000,0xbf440000,0x3fedbfb5,0xbf443fb5,0x3f443fb5,0xbfed3fb5,0xbfed0000,0x3f440000,0x3f44c000,0xbfed4000,
0x3f443fb5,0x3fedbfb5,0xbfed3fb5,0xbf443fb5,0xbfe20000,0xbf150000,0x3f71c000,0x3ff5c000,0x3e493fd5,0xbfc63f8e,0xbfff3f8e,0x3fa2bfd5,
0x3fc6bfed,0xbfff3fed,0x3fa23f44,0x3e49bf44,0xbff53ec8,0xbfe23ffb,0x3f15bffb,0xbf713ec8,0x3f8ec000,0x3ffbc000,0x3fd50000,0x3ec80000,
0xbffb3f44,0x3fd5bfed,0x3ec8bfed,0x3f8ebf44,0x3ec83fb5,0x3f8ebfb5,0xbffb3fb5,0x3fd5bfb5,0x3fd5bfed,0x3ec8bf44,0x3f8e3f44,0x3ffbbfed,
0x3fc60000,0x3e490000,0xbfa24000,0xbfff4000,0x3f71bffb,0x3f15bec8,0x3fe2bec8,0xbff53ffb,0xbff53f44,0x3f71bf44,0x3f15bfed,0xbfe23fed,
0xbe493fd5,0x3fa2bf8e,0xbfff3f8e,0xbfc63fd5,0xc0004000,0xbfb54000,0x0,0x3fb50000,0xc0004000,0x3fb50000,0x0,0x3fb5c000,
0xc0004000,0x3fb5c000,0x0,0xbfb50000,0xc0004000,0xbfb50000,0x0,0xbfb54000,0x3e490000,0x3fc60000,0x3fffc000,0x3fa2c000,
0x3f15bec8,0x3f71bffb,0x3ff5bffb,0xbfe23ec8,0x3f71bf44,0xbff53f44,0x3fe2bfed,0xbf153fed,0x3fa2bf8e,0xbe493fd5,0x3fc6bfd5,0x3fffbf8e,
0x3ffbc000,0x3f8ec000,0xbec80000,0xbfd50000,0x3fd5bfed,0xbffb3f44,0xbf8e3f44,0xbec83fed,0x3f8ebfb5,0x3ec83fb5,0xbfd53fb5,0x3ffbbfb5,
0x3ec8bf44,0x3fd5bfed,0xbffb3fed,0xbf8ebf44,0xbf150000,0xbfe20000,0xbff54000,0xbf714000,0xbfc63f8e,0x3e493fd5,0xbfa23fd5,0x3fffbf8e,
0xbfff3fed,0x3fc6bfed,0xbe493f44,0xbfa2bf44,0xbfe23ffb,0xbff53ec8,0x3f71bec8,0xbf153ffb,0xbfed4000,0xbf444000,0x3f440000,0x3fed0000,
0xbf443fb5,0x3fedbfb5,0x3fedbfb5,0xbf44bfb5,0x3f440000,0xbfed0000,0x3fedc000,0xbf444000,0x3fedbfb5,0x3f443fb5,0x3f44bfb5,0x3fedbfb5,
0x3f710000,0x3ff50000,0x3fe2c000,0x3f15c000,0x3fffbfd5,0xbfa2bf8e,0x3e49bf8e,0xbfc63fd5,0x3fa2bfed,0x3e493fed,0xbfc63f44,0x3fffbf44,
0xbf15bec8,0x3f71bffb,0xbff53ffb,0xbfe2bec8,0x3fd5c000,0x3ec8c000,0xbf8e0000,0xbffb0000,0xbec8bf44,0xbf8e3fed,0xbffb3fed,0x3fd53f44,
0xbffb3fb5,0x3fd5bfb5,0xbec83fb5,0xbf8ebfb5,0xbf8e3fed,0xbffb3f44,0x3fd5bf44,0x3ec83fed,0xbfa20000,0xbfff0000,0xbfc64000,0xbe494000,
0xbfe23ffb,0x3ff53ec8,0x3f713ec8,0x3f15bffb,0x3f153f44,0xbfe2bf44,0x3ff5bfed,0xbf713fed,0x3fffbfd5,0x3fc63f8e,0xbe49bf8e,0x3fa2bfd5,
0x4000,0x3fb54000,0x40000000,0x3fb50000,0xc000,0xbfb50000,0xc0000000,0x3fb54000,0x4000,0xbfb5c000,0x40000000,0xbfb50000,
0xc000,0x3fb50000,0xc0000000,0xbfb5c000,0x3fff0000,0x3fa20000,0xbe49c000,0xbfc6c000,0xbff53ec8,0x3fe23ffb,0x3f153ffb,0x3f71bec8,
0x3fe2bf44,0xbf153f44,0xbf71bfed,0x3ff53fed,0xbfc63f8e,0xbfffbfd5,0x3fa23fd5,0xbe493f8e,0xbec8c000,0xbfd5c000,0xbffb0000,0xbf8e0000,
0x3f8e3fed,0x3ec8bf44,0x3fd5bf44,0xbffbbfed,0xbfd5bfb5,0x3ffb3fb5,0xbf8e3fb5,0xbec8bfb5,0x3ffb3f44,0x3f8e3fed,0x3ec8bfed,0x3fd53f44,
0xbff50000,0xbf710000,0x3f154000,0x3fe24000,0x3fa2bf8e,0xbfffbfd5,0xbfc6bfd5,0x3e493f8e,0xbe493fed,0xbfa2bfed,0x3fff3f44,0xbfc6bf44,
0xbf71bffb,0x3f15bec8,0xbfe23ec8,0xbff5bffb,0x3f444000,0x3fed4000,0x3fed0000,0x3f440000,0xbfedbfb5,0x3f443fb5,0xbf443fb5,0x3fed3fb5,
0x3fed0000,0xbf440000,0xbf44c000,0x3fed4000,0xbf443fb5,0xbfedbfb5,0x3fed3fb5,0x3f443fb5,0x3fe20000,0x3f150000,0xbf71c000,0xbff5c000,
0xbe493fd5,0x3fc63f8e,0x3fff3f8e,0xbfa2bfd5,0xbfc6bfed,0x3fff3fed,0xbfa23f44,0xbe49bf44,0x3ff53ec8,0x3fe23ffb,0xbf15bffb,0x3f713ec8,
0xbf8ec000,0xbffbc000,0xbfd50000,0xbec80000,0x3ffb3f44,0xbfd5bfed,0xbec8bfed,0xbf8ebf44,0xbec83fb5,0xbf8ebfb5,0x3ffb3fb5,0xbfd5bfb5,
0xbfd5bfed,0xbec8bf44,0xbf8e3f44,0xbffbbfed,0xbfc60000,0xbe490000,0x3fa24000,0x3fff4000,0xbf71bffb,0xbf15bec8,0xbfe2bec8,0x3ff53ffb,
0x3ff53f44,0xbf71bf44,0xbf15bfed,0x3fe23fed,0x3e493fd5,0xbfa2bf8e,0x3fff3f8e,0x3fc63fd5,0x40004000,0x3fb54000,0x0,0xbfb50000,
0x40004000,0xbfb50000,0x0,0xbfb5c000,0x40004000,0xbfb5c000,0x0,0x3fb50000,0x40004000,0x3fb50000,0x0,0x3fb54000,
0xbfc6bfb5,0xbfffbfb5,0xbfa2bfb5,0x3e49bfb5,0xbfe2bfd5,0x3f15bf8e,0xbf71bf8e,0x3ff53fd5,0xbff5bfed,0x3fe23fed,0xbf15bf44,0xbf713f44,
0xbfffbffb,0xbfa23ec8,0xbe49bec8,0xbfc6bffb,0x3ec80000,0x3fd50000,0x3ffb4000,0x3f8e4000,0x3f8e3f44,0x3ec83fed,0x3fd53fed,0xbffbbf44,
0x3fd53fb5,0xbffbbfb5,0x3f8e3fb5,0x3ec8bfb5,0x3ffb3fed,0x3f8ebf44,0x3ec83f44,0x3fd53fed,0x3f713fb5,0xbf153fb5,0xbfe2bfb5,0xbff5bfb5,
0xbe493ec8,0xbfa2bffb,0xbfffbffb,0x3fc6bec8,0xbfa2bf44,0x3fff3f44,0xbfc6bfed,0x3e493fed,0xbff5bfd5,0xbf713f8e,0xbf15bf8e,0xbfe2bfd5,
0xbfedc000,0xbf44c000,0x3f440000,0x3fed0000,0xbf44bfb5,0x3fed3fb5,0x3fed3fb5,0xbf443fb5,0x3f440000,0xbfed0000,0x3fed4000,0xbf44c000,
0x3fed3fb5,0x3f44bfb5,0x3f443fb5,0x3fed3fb5,0x3ff53fb5,0x3fe23fb5,0x3f153fb5,0xbf713fb5,0x3fc63ffb,0xbfffbec8,0xbfa2bec8,0xbe49bffb,
0xbe493f44,0x3fc6bf44,0xbfffbfed,0x3fa23fed,0xbfe2bf8e,0xbf153fd5,0xbf71bfd5,0xbff5bf8e,0xbf8e0000,0xbffb0000,0xbfd5c000,0xbec8c000,
0xbffbbfed,0x3fd5bf44,0x3ec8bf44,0x3f8e3fed,0xbec8bfb5,0xbf8e3fb5,0x3ffb3fb5,0xbfd5bfb5,0x3fd53f44,0x3ec8bfed,0x3f8e3fed,0x3ffb3f44,
0xbe49bfb5,0x3fa2bfb5,0x3fff3fb5,0x3fc63fb5,0x3ff53f8e,0xbf713fd5,0x3f153fd5,0xbfe2bf8e,0x3f713fed,0x3f15bfed,0xbfe2bf44,0x3ff53f44,
0xbfc6bec8,0xbe493ffb,0xbfa2bffb,0xbfffbec8,0x4000,0xbfb54000,0xc0000000,0xbfb50000,0xc000,0x3fb50000,0x40000000,0xbfb54000,
0x4000,0x3fb5c000,0xc0000000,0x3fb50000,0xc000,0xbfb50000,0x40000000,0x3fb5c000,0xbfa2bfb5,0x3e49bfb5,0x3fc6bfb5,0x3fffbfb5,
0x3f713fd5,0xbff53f8e,0xbfe23f8e,0x3f15bfd5,0xbf15bfed,0xbf713fed,0x3ff5bf44,0xbfe23f44,0x3e493ffb,0x3fc6bec8,0xbfff3ec8,0xbfa23ffb,
0x3ffb0000,0x3f8e0000,0xbec84000,0xbfd54000,0xbfd5bf44,0x3ffbbfed,0x3f8ebfed,0x3ec83f44,0x3f8e3fb5,0x3ec8bfb5,0xbfd53fb5,0x3ffbbfb5,
0xbec8bfed,0xbfd53f44,0x3ffbbf44,0x3f8ebfed,0xbfe23fb5,0xbff53fb5,0xbf71bfb5,0x3f15bfb5,0x3fffbec8,0xbfc63ffb,0xbe493ffb,0xbfa23ec8,
0xbfc6bf44,0x3e493f44,0x3fa2bfed,0xbfff3fed,0x3f153fd5,0x3fe2bf8e,0xbff53f8e,0xbf713fd5,0x3f44c000,0x3fedc000,0x3fed0000,0x3f440000,
0xbfed3fb5,0x3f44bfb5,0xbf44bfb5,0x3fedbfb5,0x3fed0000,0xbf440000,0xbf444000,0x3fedc000,0xbf44bfb5,0xbfed3fb5,0x3fedbfb5,0x3f44bfb5,
0x3f153fb5,0xbf713fb5,0xbff53fb5,0xbfe23fb5,0x3fa2bffb,0x3e493ec8,0x3fc63ec8,0xbfff3ffb,0xbfff3f44,0x3fa2bf44,0x3e49bfed,0xbfc63fed,
0x3f713f8e,0x3ff5bfd5,0xbfe23fd5,0xbf153f8e,0xbfd50000,0xbec80000,0x3f8ec000,0x3ffbc000,0xbec83fed,0xbf8e3f44,0xbffb3f44,0x3fd5bfed,
0x3ffbbfb5,0xbfd53fb5,0x3ec83fb5,0x3f8ebfb5,0xbf8ebf44,0xbffb3fed,0x3fd5bfed,0x3ec8bf44,0x3fffbfb5,0x3fc6bfb5,0x3e493fb5,0xbfa23fb5,
0xbf15bf8e,0x3fe2bfd5,0x3ff5bfd5,0xbf713f8e,0xbfe23fed,0x3ff5bfed,0xbf71bf44,0xbf153f44,0x3fa23ec8,0x3fffbffb,0xbfc63ffb,0xbe493ec8,
0xc0004000,0xbfb54000,0x0,0x3fb50000,0xc0004000,0x3fb50000,0x0,0x3fb5c000,0xc0004000,0x3fb5c000,0x0,0xbfb50000,
0xc0004000,0xbfb50000,0x0,0xbfb54000,0x3fc6bfb5,0x3fffbfb5,0x3fa2bfb5,0xbe49bfb5,0x3fe2bfd5,0xbf15bf8e,0x3f71bf8e,0xbff53fd5,
0x3ff5bfed,0xbfe23fed,0x3f15bf44,0x3f713f44,0x3fffbffb,0x3fa23ec8,0x3e49bec8,0x3fc6bffb,0xbec80000,0xbfd50000,0xbffb4000,0xbf8e4000,
0xbf8e3f44,0xbec83fed,0xbfd53fed,0x3ffbbf44,0xbfd53fb5,0x3ffbbfb5,0xbf8e3fb5,0xbec8bfb5,0xbffb3fed,0xbf8ebf44,0xbec83f44,0xbfd53fed,
0xbf713fb5,0x3f153fb5,0x3fe2bfb5,0x3ff5bfb5,0x3e493ec8,0x3fa2bffb,0x3fffbffb,0xbfc6bec8,0x3fa2bf44,0xbfff3f44,0x3fc6bfed,0xbe493fed,
0x3ff5bfd5,0x3f713f8e,0x3f15bf8e,0x3fe2bfd5,0x3fedc000,0x3f44c000,0xbf440000,0xbfed0000,0x3f44bfb5,0xbfed3fb5,0xbfed3fb5,0x3f443fb5,
0xbf440000,0x3fed0000,0xbfed4000,0x3f44c000,0xbfed3fb5,0xbf44bfb5,0xbf443fb5,0xbfed3fb5,0xbff53fb5,0xbfe23fb5,0xbf153fb5,0x3f713fb5,
0xbfc63ffb,0x3fffbec8,0x3fa2bec8,0x3e49bffb,0x3e493f44,0xbfc6bf44,0x3fffbfed,0xbfa23fed,0x3fe2bf8e,0x3f153fd5,0x3f71bfd5,0x3ff5bf8e,
0x3f8e0000,0x3ffb0000,0x3fd5c000,0x3ec8c000,0x3ffbbfed,0xbfd5bf44,0xbec8bf44,0xbf8e3fed,0x3ec8bfb5,0x3f8e3fb5,0xbffb3fb5,0x3fd5bfb5,
0xbfd53f44,0xbec8bfed,0xbf8e3fed,0xbffb3f44,0x3e49bfb5,0xbfa2bfb5,0xbfff3fb5,0xbfc63fb5,0xbff53f8e,0x3f713fd5,0xbf153fd5,0x3fe2bf8e,
0xbf713fed,0xbf15bfed,0x3fe2bf44,0xbff53f44,0x3fc6bec8,0x3e493ffb,0x3fa2bffb,0x3fffbec8,0x4000,0x3fb54000,0x40000000,0x3fb50000,
0xc000,0xbfb50000,0xc0000000,0x3fb54000,0x4000,0xbfb5c000,0x40000000,0xbfb50000,0xc000,0x3fb50000,0xc0000000,0xbfb5c000,
0x3fa2bfb5,0xbe49bfb5,0xbfc6bfb5,0xbfffbfb5,0xbf713fd5,0x3ff53f8e,0x3fe23f8e,0xbf15bfd5,0x3f15bfed,0x3f713fed,0xbff5bf44,0x3fe23f44,
0xbe493ffb,0xbfc6bec8,0x3fff3ec8,0x3fa23ffb,0xbffb0000,0xbf8e0000,0x3ec84000,0x3fd54000,0x3fd5bf44,0xbffbbfed,0xbf8ebfed,0xbec83f44,
0xbf8e3fb5,0xbec8bfb5,0x3fd53fb5,0xbffbbfb5,0x3ec8bfed,0x3fd53f44,0xbffbbf44,0xbf8ebfed,0x3fe23fb5,0x3ff53fb5,0x3f71bfb5,0xbf15bfb5,
0xbfffbec8,0x3fc63ffb,0x3e493ffb,0x3fa23ec8,0x3fc6bf44,0xbe493f44,0xbfa2bfed,0x3fff3fed,0xbf153fd5,0xbfe2bf8e,0x3ff53f8e,0x3f713fd5,
0xbf44c000,0xbfedc000,0xbfed0000,0xbf440000,0x3fed3fb5,0xbf44bfb5,0x3f44bfb5,0xbfedbfb5,0xbfed0000,0x3f440000,0x3f444000,0xbfedc000,
0x3f44bfb5,0x3fed3fb5,0xbfedbfb5,0xbf44bfb5,0xbf153fb5,0x3f713fb5,0x3ff53fb5,0x3fe23fb5,0xbfa2bffb,0xbe493ec8,0xbfc63ec8,0x3fff3ffb,
0x3fff3f44,0xbfa2bf44,0xbe49bfed,0x3fc63fed,0xbf713f8e,0xbff5bfd5,0x3fe23fd5,0x3f153f8e,0x3fd50000,0x3ec80000,0xbf8ec000,0xbffbc000,
0x3ec83fed,0x3f8e3f44,0x3ffb3f44,0xbfd5bfed,0xbffbbfb5,0x3fd53fb5,0xbec83fb5,0xbf8ebfb5,0x3f8ebf44,0x3ffb3fed,0xbfd5bfed,0xbec8bf44,
0xbfffbfb5,0xbfc6bfb5,0xbe493fb5,0x3fa23fb5,0x3f15bf8e,0xbfe2bfd5,0xbff5bfd5,0x3f713f8e,0x3fe23fed,0xbff5bfed,0x3f71bf44,0x3f153f44,
0xbfa23ec8,0xbfffbffb,0x3fc63ffb,0x3e493ec8,0x80003f80,0x3f800000,0x80003f80,0x3f800000,0x80003f80,0x3f800000,0x80003f80,0x3f800000,
0x80003f80,0x3f800000,0x80003f80,0x3f800000,0x80003f80,0x3f800000,0x80003f80,0x3f800000,0x80003f80,0x3f800000,0x8000bf80,0xbf800000,
0x3f353f35,0x3f35bf35,0xbf35bf35,0xbf353f35,0x3f800000,0xbf80,0xbf800000,0x3f80,0x3f35bf35,0xbf35bf35,0xbf353f35,0x3f353f35,
0x80003f80,0x3f800000,0x80003f80,0x3f800000,0x3f800000,0xbf80,0x3f800000,0xbf80,0x8000bf80,0xbf800000,0x8000bf80,0xbf800000,
0xbf800000,0x3f80,0xbf800000,0x3f80,0x80003f80,0x3f800000,0x8000bf80,0xbf800000,0x3f35bf35,0xbf35bf35,0xbf353f35,0x3f353f35,
0xbf800000,0x3f80,0x3f800000,0xbf80,0x3f353f35,0x3f35bf35,0xbf35bf35,0xbf353f35,0x80003f80,0x3f800000,0x80003f80,0x3f800000,
0x8000bf80,0xbf800000,0x8000bf80,0xbf800000,0x80003f80,0x3f800000,0x80003f80,0x3f800000,0x8000bf80,0xbf800000,0x8000bf80,0xbf800000,
0x80003f80,0x3f800000,0x8000bf80,0xbf800000,0xbf35bf35,0xbf353f35,0x3f353f35,0x3f35bf35,0x3f800000,0xbf80,0xbf800000,0x3f80,
0xbf353f35,0x3f353f35,0x3f35bf35,0xbf35bf35,0x80003f80,0x3f800000,0x80003f80,0x3f800000,0xbf800000,0x3f80,0xbf800000,0x3f80,
0x8000bf80,0xbf800000,0x8000bf80,0xbf800000,0x3f800000,0xbf80,0x3f800000,0xbf80,0x80003f80,0x3f800000,0x8000bf80,0xbf800000,
0xbf353f35,0x3f353f35,0x3f35bf35,0xbf35bf35,0xbf800000,0x3f80,0x3f800000,0xbf80,0xbf35bf35,0xbf353f35,0x3f353f35,0x3f35bf35,
0x3f803f80,0x80008000,0x80008000,0xbf80bf80,0x3f803f80,0x80008000,0x80008000,0xbf80bf80,0x3f803f80,0x80008000,0x80008000,0xbf80bf80,
0x3f803f80,0x80008000,0x80008000,0xbf80bf80,0x3f353f80,0x3f358000,0x3f358000,0xbf35bf80,0xbf350000,0x3f353f80,0x3f353f80,0x3f358000,
0xbf35bf80,0xbf358000,0xbf358000,0x3f353f80,0x3f350000,0xbf35bf80,0xbf35bf80,0xbf358000,0x3f80,0x3f808000,0x3f808000,0x8000bf80,
0xbf80,0xbf808000,0xbf808000,0x80003f80,0x3f80,0x3f808000,0x3f808000,0x8000bf80,0xbf80,0xbf808000,0xbf808000,0x80003f80,
0xbf353f80,0x3f358000,0x3f358000,0x3f35bf80,0x3f350000,0x3f35bf80,0x3f35bf80,0xbf358000,0x3f35bf80,0xbf358000,0xbf358000,0xbf353f80,
0xbf350000,0xbf353f80,0xbf353f80,0x3f358000,0xbf803f80,0x80008000,0x80008000,0x3f80bf80,0xbf803f80,0x80008000,0x80008000,0x3f80bf80,
0xbf803f80,0x80008000,0x80008000,0x3f80bf80,0xbf803f80,0x80008000,0x80008000,0x3f80bf80,0xbf353f80,0xbf358000,0xbf358000,0x3f35bf80,
0x3f350000,0xbf353f80,0xbf353f80,0xbf358000,0x3f35bf80,0x3f358000,0x3f358000,0xbf353f80,0xbf350000,0x3f35bf80,0x3f35bf80,0x3f358000,
0x3f80,0xbf808000,0xbf808000,0x8000bf80,0xbf80,0x3f808000,0x3f808000,0x80003f80,0x3f80,0xbf808000,0xbf808000,0x8000bf80,
0xbf80,0x3f808000,0x3f808000,0x80003f80,0x3f353f80,0xbf358000,0xbf358000,0xbf35bf80,0xbf350000,0xbf35bf80,0xbf35bf80,0x3f358000,
0xbf35bf80,0x3f358000,0x3f358000,0x3f353f80,0x3f350000,0x3f353f80,0x3f353f80,0xbf358000,0x3f800000,0x0,0x3f800000,0x0,
0x3f800000,0x0,0x3f800000,0x0,0x3f800000,0x0,0x3f800000,0x0,0x3f800000,0x0,0x3f800000,0x0,
0x3f800000,0x0,0x3f7fb10f,0xbd48fb30,0x3f7ec46d,0xbdc8bd36,0x3f7d3aac,0xbe164083,0x3f7b14be,0xbe47c5c2,0x3f7853f8,0xbe78cfcc,
0x3f74fa0b,0xbe94a031,0x3f710908,0xbeac7cd4,0x3f800000,0x0,0x3f7ec46d,0xbdc8bd36,0x3f7b14be,0xbe47c5c2,0x3f74fa0b,0xbe94a031,
0x3f6c835e,0xbec3ef15,0x3f61c598,0xbef15aea,0x3f54db31,0xbf0e39da,0x3f45e403,0xbf226799,0x3f800000,0x0,0x3f7d3aac,0xbe164083,
0x3f74fa0b,0xbe94a031,0x3f676bd8,0xbedae880,0x3f54db31,0xbf0e39da,0x3f3daef9,0xbf2beb4a,0x3f226799,0xbf45e403,0x3f039c3d,0xbf5b941a,
0x3f800000,0x0,0x3f7b14be,0xbe47c5c2,0x3f6c835e,0xbec3ef15,0x3f54db31,0xbf0e39da,0x3f3504f3,0xbf3504f3,0x3f0e39da,0xbf54db31,
0x3ec3ef15,0xbf6c835e,0x3e47c5c2,0xbf7b14be,0x3f800000,0x0,0x3f7853f8,0xbe78cfcc,0x3f61c598,0xbef15aea,0x3f3daef9,0xbf2beb4a,
0x3f0e39da,0xbf54db31,0x3eac7cd4,0xbf710908,0x3dc8bd36,0xbf7ec46d,0xbe164083,0xbf7d3aac,0x3f800000,0x0,0x3f74fa0b,0xbe94a031,
0x3f54db31,0xbf0e39da,0x3f226799,0xbf45e403,0x3ec3ef15,0xbf6c835e,0x3dc8bd36,0xbf7ec46d,0xbe47c5c2,0xbf7b14be,0xbef15aea,0xbf61c598,
0x3f800000,0x0,0x3f710908,0xbeac7cd4,0x3f45e403,0xbf226799,0x3f039c3d,0xbf5b941a,0x3e47c5c2,0xbf7b14be,0xbe164083,0xbf7d3aac,
0xbef15aea,0xbf61c598,0xbf3daef9,0xbf2beb4a,0x3f800000,0x0,0x3f800000,0x0,0x3f800000,0x0,0x3f800000,0x0,
0x3f800000,0x0,0x3f800000,0x0,0x3f800000,0x0,0x3f800000,0x0,0x3f6c835e,0xbec3ef15,0x3f676bd8,0xbedae880,
0x3f61c598,0xbef15aea,0x3f5b941a,0xbf039c3d,0x3f54db31,0xbf0e39da,0x3f4d9f02,0xbf187fc0,0x3f45e403,0xbf226799,0x3f3daef9,0xbf2beb4a,
0x3f3504f3,0xbf3504f3,0x3f226799,0xbf45e403,0x3f0e39da,0xbf54db31,0x3ef15aea,0xbf61c598,0x3ec3ef15,0xbf6c835e,0x3e94a031,0xbf74fa0b,
0x3e47c5c2,0xbf7b14be,0x3dc8bd36,0xbf7ec46d,0x3ec3ef15,0xbf6c835e,0x3e78cfcc,0xbf7853f8,0x3dc8bd36,0xbf7ec46d,0xbd48fb30,0xbf7fb10f,
0xbe47c5c2,0xbf7b14be,0xbeac7cd4,0xbf710908,0xbef15aea,0xbf61c598,0xbf187fc0,0xbf4d9f02,0x0,0xbf800000,0xbe47c5c2,0xbf7b14be,
0xbec3ef15,0xbf6c835e,0xbf0e39da,0xbf54db31,0xbf3504f3,0xbf3504f3,0xbf54db31,0xbf0e39da,0xbf6c835e,0xbec3ef15,0xbf7b14be,0xbe47c5c2,
0xbec3ef15,0xbf6c835e,0xbf187fc0,0xbf4d9f02,0xbf45e403,0xbf226799,0xbf676bd8,0xbedae880,0xbf7b14be,0xbe47c5c2,0xbf7fb10f,0x3d48fb30,
0xbf74fa0b,0x3e94a031,0xbf5b941a,0x3f039c3d,0xbf3504f3,0xbf3504f3,0xbf61c598,0xbef15aea,0xbf7b14be,0xbe47c5c2,0xbf7ec46d,0x3dc8bd36,
0xbf6c835e,0x3ec3ef15,0xbf45e403,0x3f226799,0xbf0e39da,0x3f54db31,0xbe94a031,0x3f74fa0b,0xbf6c835e,0xbec3ef15,0xbf7fb10f,0xbd48fb30,
0xbf74fa0b,0x3e94a031,0xbf4d9f02,0x3f187fc0,0xbf0e39da,0x3f54db31,0xbe78cfcc,0x3f7853f8,0x3dc8bd36,0x3f7ec46d,0x3edae880,0x3f676bd8,
0x80003f80,0x3f800000,0x3f800000,0xbf80,0x3ec43f6d,0x3f6dbec4,0x3f6dbec4,0xbec4bf6d,0x3f353f35,0x3f35bf35,0x3f35bf35,0xbf35bf35,
0x3f6d3ec4,0x3ec4bf6d,0x3ec4bf6d,0xbf6dbec4,0x80003f80,0x3f800000,0xbf800000,0x3f80,0x3f6d3ec4,0x3ec4bf6d,0xbec43f6d,0x3f6d3ec4,
0x3f35bf35,0xbf35bf35,0x3f353f35,0x3f35bf35,0xbec4bf6d,0xbf6d3ec4,0x3f6dbec4,0xbec4bf6d,0x80003f80,0x3f800000,0x3f800000,0xbf80,
0x3f6dbec4,0xbec4bf6d,0xbec4bf6d,0xbf6d3ec4,0xbf35bf35,0xbf353f35,0xbf353f35,0x3f353f35,0xbec43f6d,0x3f6d3ec4,0x3f6d3ec4,0x3ec4bf6d,
0x80003f80,0x3f800000,0xbf800000,0x3f80,0x3ec4bf6d,0xbf6dbec4,0x3f6d3ec4,0x3ec4bf6d,0xbf353f35,0x3f353f35,0xbf35bf35,0xbf353f35,
0x3f6dbec4,0xbec4bf6d,0x3ec43f6d,0x3f6dbec4,0x80003f80,0x3f800000,0x3f800000,0xbf80,0xbec4bf6d,0xbf6d3ec4,0xbf6d3ec4,0x3ec43f6d,
0x3f353f35,0x3f35bf35,0x3f35bf35,0xbf35bf35,0xbf6dbec4,0xbec43f6d,0xbec43f6d,0x3f6d3ec4,0x80003f80,0x3f800000,0xbf800000,0x3f80,
0xbf6dbec4,0xbec43f6d,0x3ec4bf6d,0xbf6dbec4,0x3f35bf35,0xbf35bf35,0x3f353f35,0x3f35bf35,0x3ec43f6d,0x3f6dbec4,0xbf6d3ec4,0x3ec43f6d,
0x80003f80,0x3f800000,0x3f800000,0xbf80,0xbf6d3ec4,0x3ec43f6d,0x3ec43f6d,0x3f6dbec4,0xbf35bf35,0xbf353f35,0xbf353f35,0x3f353f35,
0x3ec4bf6d,0xbf6dbec4,0xbf6dbec4,0xbec43f6d,0x80003f80,0x3f800000,0xbf800000,0x3f80,0xbec43f6d,0x3f6d3ec4,0xbf6dbec4,0xbec43f6d,
0xbf353f35,0x3f353f35,0xbf35bf35,0xbf353f35,0xbf6d3ec4,0x3ec43f6d,0xbec4bf6d,0xbf6d3ec4,0x3f803f80,0x80008000,0x80008000,0xbf80bf80,
0x3f803f80,0x80008000,0x80008000,0xbf80bf80,0x3f803f80,0x80008000,0x80008000,0xbf80bf80,0x3f803f80,0x80008000,0x80008000,0xbf80bf80,
0x3ec43f6d,0x3f6d3ec4,0x3f6d3ec4,0xbec4bf6d,0xbf6dbec4,0x3ec43f6d,0x3ec43f6d,0x3f6d3ec4,0xbec4bf6d,0xbf6dbec4,0xbf6dbec4,0x3ec43f6d,
0x3f6d3ec4,0xbec4bf6d,0xbec4bf6d,0xbf6dbec4,0xbf353f35,0x3f353f35,0x3f353f35,0x3f35bf35,0x3f35bf35,0xbf35bf35,0xbf35bf35,0xbf353f35,
0xbf353f35,0x3f353f35,0x3f353f35,0x3f35bf35,0x3f35bf35,0xbf35bf35,0xbf35bf35,0xbf353f35,0xbf6d3ec4,0xbec43f6d,0xbec43f6d,0x3f6dbec4,
0xbec43f6d,0x3f6dbec4,0x3f6dbec4,0x3ec4bf6d,0x3f6dbec4,0x3ec4bf6d,0x3ec4bf6d,0xbf6d3ec4,0x3ec4bf6d,0xbf6d3ec4,0xbf6d3ec4,0xbec43f6d,
0x0,0xbf803f80,0xbf803f80,0x80008000,0x0,0xbf803f80,0xbf803f80,0x80008000,0x0,0xbf803f80,0xbf803f80,0x80008000,
0x0,0xbf803f80,0xbf803f80,0x80008000,0x3f6dbec4,0xbec43f6d,0xbec43f6d,0xbf6d3ec4,0x3ec4bf6d,0x3f6dbec4,0x3f6dbec4,0xbec43f6d,
0xbf6d3ec4,0x3ec4bf6d,0x3ec4bf6d,0x3f6dbec4,0xbec43f6d,0xbf6d3ec4,0xbf6d3ec4,0x3ec4bf6d,0x3f35bf35,0x3f353f35,0x3f353f35,0xbf353f35,
0xbf353f35,0xbf35bf35,0xbf35bf35,0x3f35bf35,0x3f35bf35,0x3f353f35,0x3f353f35,0xbf353f35,0xbf353f35,0xbf35bf35,0xbf35bf35,0x3f35bf35,
0xbec4bf6d,0x3f6d3ec4,0x3f6d3ec4,0x3ec43f6d,0x3f6d3ec4,0x3ec43f6d,0x3ec43f6d,0xbf6dbec4,0x3ec43f6d,0xbf6dbec4,0xbf6dbec4,0xbec4bf6d,
0xbf6dbec4,0xbec4bf6d,0xbec4bf6d,0x3f6d3ec4,0x3f800000,0x0,0x3f7fec43,0xbcc90ab0,0x3f7fb10f,0xbd48fb30,0x3f7f4e6d,0xbd96a905,
0x3f7ec46d,0xbdc8bd36,0x3f7e1324,0xbdfab273,0x3f7d3aac,0xbe164083,0x3f7c3b28,0xbe2f10a2,0x3f800000,0x0,0x3f7f4e6d,0xbd96a905,
0x3f7d3aac,0xbe164083,0x3f79c79d,0xbe605c13,0x3f74fa0b,0xbe94a031,0x3f6ed89e,0xbeb8442a,0x3f676bd8,0xbedae880,0x3f5ebe05,0xbefc5d27,
0x3f800000,0x0,0x3f7e1324,0xbdfab273,0x3f7853f8,0xbe78cfcc,0x3f6ed89e,0xbeb8442a,0x3f61c598,0xbef15aea,0x3f514d3d,0xbf13682a,
0x3f3daef9,0xbf2beb4a,0x3f273656,0xbf41d870,0x3f800000,0x0,0x3f7c3b28,0xbe2f10a2,0x3f710908,0xbeac7cd4,0x3f5ebe05,0xbefc5d27,
0x3f45e403,0xbf226799,0x3f273656,0xbf41d870,0x3f039c3d,0xbf5b941a,0x3eb8442a,0xbf6ed89e,0x3f800000,0x0,0x3f79c79d,0xbe605c13,
0x3f676bd8,0xbedae880,0x3f49d112,0xbf1d7fd1,0x3f226799,0xbf45e403,0x3ee63375,0xbf64aa59,0x3e78cfcc,0xbf7853f8,0x3cc90ab0,0xbf7fec43,
0x3f800000,0x0,0x3f76ba07,0xbe888e93,0x3f5b941a,0xbf039c3d,0x3f3085bb,0xbf396842,0x3ef15aea,0xbf61c598,0x3e605c13,0xbf79c79d,
0xbd48fb30,0xbf7fb10f,0xbea09ae5,0xbf731447,0x3f800000,0x0,0x3f731447,0xbea09ae5,0x3f4d9f02,0xbf187fc0,0x3f13682a,0xbf514d3d,
0x3e94a031,0xbf74fa0b,0xbcc90ab0,0xbf7fec43,0xbeac7cd4,0xbf710908,0xbf1d7fd1,0xbf49d112,0x3f800000,0x0,0x3f6ed89e,0xbeb8442a,
0x3f3daef9,0xbf2beb4a,0x3ee63375,0xbf64aa59,0x3dc8bd36,0xbf7ec46d,0xbe888e93,0xbf76ba07,0xbf187fc0,0xbf4d9f02,0xbf584853,0xbf08f59b,
0x3f7b14be,0xbe47c5c2,0x3f79c79d,0xbe605c13,0x3f7853f8,0xbe78cfcc,0x3f76ba07,0xbe888e93,0x3f74fa0b,0xbe94a031,0x3f731447,0xbea09ae5,
0x3f710908,0xbeac7cd4,0x3f6ed89e,0xbeb8442a,0x3f54db31,0xbf0e39da,0x3f49d112,0xbf1d7fd1,0x3f3daef9,0xbf2beb4a,0x3f3085bb,0xbf396842,
0x3f226799,0xbf45e403,0x3f13682a,0xbf514d3d,0x3f039c3d,0xbf5b941a,0x3ee63375,0xbf64aa59,0x3f0e39da,0xbf54db31,0x3ee63375,0xbf64aa59,
0x3eac7cd4,0xbf710908,0x3e605c13,0xbf79c79d,0x3dc8bd36,0xbf7ec46d,0xbcc90ab0,0xbf7fec43,0xbe164083,0xbf7d3aac,0xbe888e93,0xbf76ba07,
0x3e47c5c2,0xbf7b14be,0x3cc90ab0,0xbf7fec43,0xbe164083,0xbf7d3aac,0xbea09ae5,0xbf731447,0xbef15aea,0xbf61c598,0xbf1d7fd1,0xbf49d112,
0xbf3daef9,0xbf2beb4a,0xbf584853,0xbf08f59b,0xbe47c5c2,0xbf7b14be,0xbecf7bca,0xbf6a09a7,0xbf187fc0,0xbf4d9f02,0xbf41d870,0xbf273656,
0xbf61c598,0xbef15aea,0xbf76ba07,0xbe888e93,0xbf7fb10f,0xbd48fb30,0xbf7c3b28,0x3e2f10a2,0xbf0e39da,0xbf54db31,0xbf41d870,0xbf273656,
0xbf676bd8,0xbedae880,0xbf7c3b28,0xbe2f10a2,0xbf7ec46d,0x3dc8bd36,0xbf6ed89e,0x3eb8442a,0xbf4d9f02,0x3f187fc0,0xbf1d7fd1,0x3f49d112,
0xbf54db31,0xbf0e39da,0xbf76ba07,0xbe888e93,0xbf7fb10f,0x3d48fb30,0xbf6ed89e,0x3eb8442a,0xbf45e403,0x3f226799,0xbf08f59b,0x3f584853,
0xbe78cfcc,0x3f7853f8,0x3d96a905,0x3f7f4e6d,0xbf7b14be,0xbe47c5c2,0xbf7c3b28,0x3e2f10a2,0xbf5b941a,0x3f039c3d,0xbf1d7fd1,0x3f49d112,
0xbe94a031,0x3f74fa0b,0x3d96a905,0x3f7f4e6d,0x3edae880,0x3f676bd8,0x3f396842,0x3f3085bb,0x80003f80,0x80003f80,0x80003f80,0x80003f80,
0x80003f80,0x80003f80,0x80003f80,0x80003f80,0x80003f80,0x80003f80,0x80003f80,0x80003f80,0x80003f80,0x80003f80,0x80003f80,0x80003f80,
0x3f800000,0x3f800000,0x3f800000,0x3f800000,0x3f800000,0x3f800000,0x3f800000,0x3f800000,0x3f800000,0x3f800000,0x3f800000,0x3f800000,
0x3f800000,0x3f800000,0x3f800000,0x3f800000,0x80003f80,0x3f353f35,0x80003f80,0x3f353f35,0x3f800000,0x3f35bf35,0x3f800000,0x3f35bf35,
0x8000bf80,0xbf35bf35,0x8000bf80,0xbf35bf35,0xbf800000,0xbf353f35,0xbf800000,0xbf353f35,0x3f800000,0x3f35bf35,0x3f800000,0x3f35bf35,
0xbf80,0xbf35bf35,0xbf80,0xbf35bf35,0xbf800000,0xbf353f35,0xbf800000,0xbf353f35,0x3f80,0x3f353f35,0x3f80,0x3f353f35,
0x80003f80,0x3f800000,0x80003f80,0x3f800000,0x8000bf80,0xbf800000,0x8000bf80,0xbf800000,0x80003f80,0x3f800000,0x80003f80,0x3f800000,
0x8000bf80,0xbf800000,0x8000bf80,0xbf800000,0x3f800000,0xbf80,0x3f800000,0xbf80,0xbf800000,0x3f80,0xbf800000,0x3f80,
0x3f800000,0xbf80,0x3f800000,0xbf80,0xbf800000,0x3f80,0xbf800000,0x3f80,0x80003f80,0x3f35bf35,0x80003f80,0x3f35bf35,
0xbf800000,0x3f353f35,0xbf800000,0x3f353f35,0x8000bf80,0xbf353f35,0x8000bf80,0xbf353f35,0x3f800000,0xbf35bf35,0x3f800000,0xbf35bf35,
0x3f800000,0xbf35bf35,0x3f800000,0xbf35bf35,0x3f80,0x3f35bf35,0x3f80,0x3f35bf35,0xbf800000,0x3f353f35,0xbf800000,0x3f353f35,
0xbf80,0xbf353f35,0xbf80,0xbf353f35,0x80003f80,0x3ec43f6d,0x8000bf80,0xbec4bf6d,0x3f353f35,0x3f6d3ec4,0xbf35bf35,0xbf6dbec4,
0x3f800000,0x3f6dbec4,0xbf800000,0xbf6d3ec4,0x3f35bf35,0x3ec4bf6d,0xbf353f35,0xbec43f6d,0x3f800000,0x3f6dbec4,0xbf800000,0xbf6d3ec4,
0x3f35bf35,0x3ec4bf6d,0xbf353f35,0xbec43f6d,0xbf80,0xbec4bf6d,0x3f80,0x3ec43f6d,0xbf35bf35,0xbf6dbec4,0x3f353f35,0x3f6d3ec4,
0x80003f80,0x3f6d3ec4,0x8000bf80,0xbf6dbec4,0x3f35bf35,0xbec4bf6d,0xbf353f35,0x3ec43f6d,0xbf800000,0xbec43f6d,0x3f800000,0x3ec4bf6d,
0x3f353f35,0x3f6dbec4,0xbf35bf35,0xbf6d3ec4,0x3f800000,0x3ec4bf6d,0xbf800000,0xbec43f6d,0xbf35bf35,0xbf6d3ec4,0x3f353f35,0x3f6dbec4,
0x3f80,0x3f6d3ec4,0xbf80,0xbf6dbec4,0x3f35bf35,0xbec4bf6d,0xbf353f35,0x3ec43f6d,0x80003f80,0x3f6dbec4,0x8000bf80,0xbf6d3ec4,
0xbf35bf35,0xbec43f6d,0x3f353f35,0x3ec4bf6d,0x3f800000,0xbec4bf6d,0xbf800000,0x3ec43f6d,0xbf353f35,0x3f6d3ec4,0x3f35bf35,0xbf6dbec4,
0x3f800000,0xbec4bf6d,0xbf800000,0x3ec43f6d,0xbf353f35,0x3f6d3ec4,0x3f35bf35,0xbf6dbec4,0xbf80,0xbf6d3ec4,0x3f80,0x3f6dbec4,
0x3f353f35,0x3ec4bf6d,0xbf35bf35,0xbec43f6d,0x80003f80,0x3ec4bf6d,0x8000bf80,0xbec43f6d,0xbf353f35,0x3f6dbec4,0x3f35bf35,0xbf6d3ec4,
0xbf800000,0x3f6d3ec4,0x3f800000,0xbf6dbec4,0xbf35bf35,0x3ec43f6d,0x3f353f35,0xbec4bf6d,0x3f800000,0xbf6dbec4,0xbf800000,0x3f6d3ec4,
0x3f353f35,0xbec4bf6d,0xbf35bf35,0x3ec43f6d,0x3f80,0x3ec4bf6d,0xbf80,0xbec43f6d,0xbf353f35,0x3f6dbec4,0x3f35bf35,0xbf6d3ec4,
0x80003f80,0x8000bf80,0x80003f80,0x8000bf80,0x80003f80,0x8000bf80,0x80003f80,0x8000bf80,0x80003f80,0x8000bf80,0x80003f80,0x8000bf80,
0x80003f80,0x8000bf80,0x80003f80,0x8000bf80,0x3f800000,0xbf800000,0x3f800000,0xbf800000,0x3f800000,0xbf800000,0x3f800000,0xbf800000,
0x3f800000,0xbf800000,0x3f800000,0xbf800000,0x3f800000,0xbf800000,0x3f800000,0xbf800000,0x80003f80,0xbf35bf35,0x80003f80,0xbf35bf35,
0x3f800000,0xbf353f35,0x3f800000,0xbf353f35,0x8000bf80,0x3f353f35,0x8000bf80,0x3f353f35,0xbf800000,0x3f35bf35,0xbf800000,0x3f35bf35,
0x3f800000,0xbf353f35,0x3f800000,0xbf353f35,0xbf80,0x3f353f35,0xbf80,0x3f353f35,0xbf800000,0x3f35bf35,0xbf800000,0x3f35bf35,
0x3f80,0xbf35bf35,0x3f80,0xbf35bf35,0x80003f80,0xbf800000,0x80003f80,0xbf800000,0x8000bf80,0x3f800000,0x8000bf80,0x3f800000,
0x80003f80,0xbf800000,0x80003f80,0xbf800000,0x8000bf80,0x3f800000,0x8000bf80,0x3f800000,0x3f800000,0x3f80,0x3f800000,0x3f80,
0xbf800000,0xbf80,0xbf800000,0xbf80,0x3f800000,0x3f80,0x3f800000,0x3f80,0xbf800000,0xbf80,0xbf800000,0xbf80,
0x80003f80,0xbf353f35,0x80003f80,0xbf353f35,0xbf800000,0xbf35bf35,0xbf800000,0xbf35bf35,0x8000bf80,0x3f35bf35,0x8000bf80,0x3f35bf35,
0x3f800000,0x3f353f35,0x3f800000,0x3f353f35,0x3f800000,0x3f353f35,0x3f800000,0x3f353f35,0x3f80,0xbf353f35,0x3f80,0xbf353f35,
0xbf800000,0xbf35bf35,0xbf800000,0xbf35bf35,0xbf80,0x3f35bf35,0xbf80,0x3f35bf35,0x80003f80,0xbec4bf6d,0x8000bf80,0x3ec43f6d,
0x3f353f35,0xbf6dbec4,0xbf35bf35,0x3f6d3ec4,0x3f800000,0xbf6d3ec4,0xbf800000,0x3f6dbec4,0x3f35bf35,0xbec43f6d,0xbf353f35,0x3ec4bf6d,
0x3f800000,0xbf6d3ec4,0xbf800000,0x3f6dbec4,0x3f35bf35,0xbec43f6d,0xbf353f35,0x3ec4bf6d,0xbf80,0x3ec43f6d,0x3f80,0xbec4bf6d,
0xbf35bf35,0x3f6d3ec4,0x3f353f35,0xbf6dbec4,0x80003f80,0xbf6dbec4,0x8000bf80,0x3f6d3ec4,0x3f35bf35,0x3ec43f6d,0xbf353f35,0xbec4bf6d,
0xbf800000,0x3ec4bf6d,0x3f800000,0xbec43f6d,0x3f353f35,0xbf6d3ec4,0xbf35bf35,0x3f6dbec4,0x3f800000,0xbec43f6d,0xbf800000,0x3ec4bf6d,
0xbf35bf35,0x3f6dbec4,0x3f353f35,0xbf6d3ec4,0x3f80,0xbf6dbec4,0xbf80,0x3f6d3ec4,0x3f35bf35,0x3ec43f6d,0xbf353f35,0xbec4bf6d,
0x80003f80,0xbf6d3ec4,0x8000bf80,0x3f6dbec4,0xbf35bf35,0x3ec4bf6d,0x3f353f35,0xbec43f6d,0x3f800000,0x3ec43f6d,0xbf800000,0xbec4bf6d,
0xbf353f35,0xbf6dbec4,0x3f35bf35,0x3f6d3ec4,0x3f800000,0x3ec43f6d,0xbf800000,0xbec4bf6d,0xbf353f35,0xbf6dbec4,0x3f35bf35,0x3f6d3ec4,
0xbf80,0x3f6dbec4,0x3f80,0xbf6d3ec4,0x3f353f35,0xbec43f6d,0xbf35bf35,0x3ec4bf6d,0x80003f80,0xbec43f6d,0x8000bf80,0x3ec4bf6d,
0xbf353f35,0xbf6d3ec4,0x3f35bf35,0x3f6dbec4,0xbf800000,0xbf6dbec4,0x3f800000,0x3f6d3ec4,0xbf35bf35,0xbec4bf6d,0x3f353f35,0x3ec43f6d,
0x3f800000,0x3f6d3ec4,0xbf800000,0xbf6dbec4,0x3f353f35,0x3ec43f6d,0xbf35bf35,0xbec4bf6d,0x3f80,0xbec43f6d,0xbf80,0x3ec4bf6d,
0xbf353f35,0xbf6d3ec4,0x3f35bf35,0x3f6dbec4,
};
constexpr int TB_F = 0, TB_E = 512, TB_P2 = 1024;

enum { C_EP = 0, C_Z1 = 32, C_Z2 = 96, C_H3 = 128, C_U = 160, C_TOTAL = 256 };
struct Scratch {
  unsigned cnt[C_TOTAL];
  uint32_t mod[6 * D_ + 384];
  uint32_t z1[120 * 5120];
  uint32_t z2[128 * 4800];
  uint32_t x1[S_ * D_ / 2];
  uint8_t h3[32 * 18 * 4096];
  uint8_t u[72 * D_ * 128];
};
__device__ __align__(1024) Scratch g_s;

#define PF2 8
#define PF2K 16
#define HOLDA 3
#define GOAT 1
#define HOLD1 0
#define XPOS 1
#define NG1 4

#define FAILCNT(k) do {} while (0)
#define CK(k) do {} while (0)
#define TS(k) do {} while (0)
#define TSC(k) do {} while (0)
struct Maps { CUtensorMap w1a, w1b, w2, x1, out, z1, z2, h3, wr, wi, wm; };
struct Params {
  const __nv_bfloat16 *x, *c, *wmod;
  Scratch* s;
  const uint4* tab;
  const __nv_bfloat16 *wr, *wi, *w1, *w2, *b1, *b2;
};

__device__ __forceinline__ uint32_t smem_u32(const void* p) { return (uint32_t)__cvta_generic_to_shared(p); }
__device__ __forceinline__ void mbar_init(uint32_t b, int c) { asm volatile("mbarrier.init.shared::cta.b64 [%0], %1;" ::"r"(b), "r"(c)); }
__device__ __forceinline__ void mbar_expect(uint32_t b, int bytes) { asm volatile("mbarrier.arrive.expect_tx.shared::cta.b64 _, [%0], %1;" ::"r"(b), "r"(bytes) : "memory"); }
__device__ __forceinline__ void mbar_arrive(uint32_t b) { asm volatile("mbarrier.arrive.shared::cta.b64 _, [%0];" ::"r"(b) : "memory"); }
#define MBAR_WAIT(SEM)                                                                                                         \
  asm volatile("{\n.reg .pred p;\n.reg .u32 it;\nmov.u32 it, 0;\nW:\nmbarrier.try_wait.parity" SEM ".shared::cta.b64 p, [%0], %1;\n" \
               "@p bra.uni D;\nadd.u32 it, it, 1;\nsetp.lt.u32 p, it, 0x400000;\n@p bra.uni W;\ntrap;\nD:\n}" ::"r"(b), "r"(ph) : "memory")
__device__ __forceinline__ void mbar_wait(uint32_t b, int ph) { MBAR_WAIT(""); }
__device__ __forceinline__ void mbar_wait_cluster(uint32_t b, int ph) { MBAR_WAIT(".acquire.cluster"); }
__device__ __forceinline__ void tma2d(uint32_t dst, const CUtensorMap* m, int c0, int c1, uint32_t bar) {
  asm volatile("cp.async.bulk.tensor.2d.shared::cluster.global.mbarrier::complete_tx::bytes [%0], [%1, {%3, %4}], [%2];" ::"r"(dst), "l"(m), "r"(bar), "r"(c0), "r"(c1) : "memory");
}
__device__ __forceinline__ uint64_t pol_ef() { uint64_t p; asm("createpolicy.fractional.L2::evict_first.b64 %0, 1.0;" : "=l"(p)); return p; }
__device__ __forceinline__ void tma3d_ef(uint32_t dst, const CUtensorMap* m, int c1, int c2, uint32_t bar) {
  asm volatile("cp.async.bulk.tensor.3d.shared::cluster.global.mbarrier::complete_tx::bytes.L2::cache_hint [%0], [%1, {%3, %4, %5}], [%2], %6;" ::"r"(dst), "l"(m), "r"(bar), "r"(0), "r"(c1), "r"(c2), "l"(pol_ef()) : "memory");
}
__device__ __forceinline__ void tma4d_ef(uint32_t dst, const CUtensorMap* m, int c2, int c3, uint32_t bar) {
  asm volatile("cp.async.bulk.tensor.4d.shared::cluster.global.mbarrier::complete_tx::bytes.L2::cache_hint [%0], [%1, {%3, %3, %4, %5}], [%2], %6;" ::"r"(dst), "l"(m), "r"(bar), "r"(0), "r"(c2), "r"(c3), "l"(pol_ef()) : "memory");
}
__device__ __forceinline__ void bulk_ld(uint32_t dst, const void* src, int bytes, uint32_t bar) {
  asm volatile("cp.async.bulk.shared::cluster.global.mbarrier::complete_tx::bytes [%0], [%1], %2, [%3];" ::"r"(dst), "l"(src), "r"(bytes), "r"(bar) : "memory");
}
__device__ __forceinline__ void bulk_st(void* dst, uint32_t src, int bytes) {
  asm volatile("cp.async.bulk.global.shared::cta.bulk_group [%0], [%1], %2;" ::"l"(dst), "r"(src), "r"(bytes) : "memory");
}
__device__ __forceinline__ void tma_st2d(const CUtensorMap* m, uint32_t src, int c0, int c1) {
  asm volatile("cp.async.bulk.tensor.2d.global.shared::cta.bulk_group [%0, {%2, %3}], [%1];" ::"l"(m), "r"(src), "r"(c0), "r"(c1) : "memory");
}
__device__ __forceinline__ void bulk_commit_wait_read() {
  asm volatile("cp.async.bulk.commit_group;" ::: "memory");
  asm volatile("cp.async.bulk.wait_group.read 0;" ::: "memory");
}
__device__ __forceinline__ void bulk_commit_wait() {
  asm volatile("cp.async.bulk.commit_group;" ::: "memory");
  asm volatile("cp.async.bulk.wait_group 0;" ::: "memory");
}
__device__ __forceinline__ void prefetch_l2(const void* p, int bytes) {
  asm volatile("cp.async.bulk.prefetch.L2.global [%0], %1;" ::"l"(p), "r"(bytes) : "memory");
}
__device__ __forceinline__ void wg_fence() { asm volatile("wgmma.fence.sync.aligned;" ::: "memory"); }
__device__ __forceinline__ void wg_commit() { asm volatile("wgmma.commit_group.sync.aligned;" ::: "memory"); }
template <int N> __device__ __forceinline__ void wg_wait() { asm volatile("wgmma.wait_group.sync.aligned %0;" ::"n"(N) : "memory"); }
template <int N> __device__ __forceinline__ void reg_fence(float (&d)[N]) {
#pragma unroll
  for (int i = 0; i < N; i++) asm volatile("" : "+f"(d[i])::"memory");
}
__device__ __forceinline__ void fence_async_smem() { asm volatile("fence.proxy.async.shared::cta;" ::: "memory"); }
__device__ __forceinline__ void fence_async_glb() { asm volatile("fence.proxy.async.global;" ::: "memory"); }
__device__ __forceinline__ uint32_t ld_rlx(const void* p) { uint32_t v; asm volatile("ld.relaxed.gpu.global.b32 %0, [%1];" : "=r"(v) : "l"(p) : "memory"); return v; }
__device__ __forceinline__ uint2 ld_rlx2(const void* p) { uint2 v; asm volatile("ld.relaxed.gpu.global.v2.b32 {%0,%1}, [%2];" : "=r"(v.x), "=r"(v.y) : "l"(p) : "memory"); return v; }
__device__ __forceinline__ uint4 ld_rlx4(const void* p) { uint4 v; asm volatile("ld.relaxed.gpu.global.v4.b32 {%0,%1,%2,%3}, [%4];" : "=r"(v.x), "=r"(v.y), "=r"(v.z), "=r"(v.w) : "l"(p) : "memory"); return v; }
__device__ __forceinline__ uint32_t ld_nc(const void* p) { uint32_t v; asm volatile("ld.global.nc.L1::no_allocate.b32 %0, [%1];" : "=r"(v) : "l"(p) : "memory"); return v; }
__device__ __forceinline__ uint32_t lds(uint32_t a) { uint32_t v; asm volatile("ld.shared.b32 %0, [%1];" : "=r"(v) : "r"(a) : "memory"); return v; }
__device__ __forceinline__ uint2 lds2(uint32_t a) { uint2 v; asm volatile("ld.shared.v2.b32 {%0,%1}, [%2];" : "=r"(v.x), "=r"(v.y) : "r"(a) : "memory"); return v; }
__device__ __forceinline__ uint4 lds4(uint32_t a) { uint4 v; asm volatile("ld.shared.v4.b32 {%0,%1,%2,%3}, [%4];" : "=r"(v.x), "=r"(v.y), "=r"(v.z), "=r"(v.w) : "r"(a) : "memory"); return v; }
__device__ __forceinline__ float lds_bf(uint32_t a) { uint32_t v; asm volatile("ld.shared.u16 %0, [%1];" : "=r"(v) : "r"(a) : "memory"); return __uint_as_float(v << 16); }
__device__ __forceinline__ void sts(uint32_t a, uint32_t v) { asm volatile("st.shared.b32 [%0], %1;" ::"r"(a), "r"(v) : "memory"); }
__device__ __forceinline__ void sts2(uint32_t a, uint32_t v0, uint32_t v1) { asm volatile("st.shared.v2.b32 [%0], {%1,%2};" ::"r"(a), "r"(v0), "r"(v1) : "memory"); }
__device__ __forceinline__ void sts4(uint32_t a, uint32_t v0, uint32_t v1, uint32_t v2, uint32_t v3) { asm volatile("st.shared.v4.b32 [%0], {%1,%2,%3,%4};" ::"r"(a), "r"(v0), "r"(v1), "r"(v2), "r"(v3) : "memory"); }
__device__ __forceinline__ void bar_sync(int id, int n) { asm volatile("bar.sync %0, %1;" ::"r"(id), "r"(n) : "memory"); }
__device__ __forceinline__ void bar_arrive(int id, int n) { asm volatile("bar.arrive %0, %1;" ::"r"(id), "r"(n) : "memory"); }
__device__ __forceinline__ void red_add(unsigned* p, unsigned v) { asm volatile("red.relaxed.gpu.global.add.u32 [%0], %1;" ::"l"(p), "r"(v) : "memory"); }
__device__ __forceinline__ bool any(bool p) { return __any_sync(0xffffffffu, p); }
constexpr int SPIN_MAX = 1 << 20;
__device__ __forceinline__ void wait_cnt(const unsigned* p, unsigned target) {
  int it = 0;
  while (any((int)(ld_rlx(p) - target) < 0) && ++it < SPIN_MAX) {}
}
__device__ __forceinline__ uint32_t pack_bf16(float lo, float hi) { uint32_t r; asm("cvt.rn.bf16x2.f32 %0, %1, %2;" : "=r"(r) : "f"(hi), "f"(lo)); return r; }
__device__ __forceinline__ float bf_lo(uint32_t v) { return __uint_as_float(v << 16); }
__device__ __forceinline__ float bf_hi(uint32_t v) { return __uint_as_float(v & 0xffff0000u); }
__device__ __forceinline__ uint32_t hadd2(uint32_t a, uint32_t b) { uint32_t r; asm("add.rn.bf16x2 %0, %1, %2;" : "=r"(r) : "r"(a), "r"(b)); return r; }
__device__ __forceinline__ uint32_t hmul2(uint32_t a, uint32_t b) { uint32_t r; asm("mul.rn.bf16x2 %0, %1, %2;" : "=r"(r) : "r"(a), "r"(b)); return r; }
__device__ __forceinline__ uint32_t hfma2(uint32_t a, uint32_t b, uint32_t c) { uint32_t r; asm("fma.rn.bf16x2 %0, %1, %2, %3;" : "=r"(r) : "r"(a), "r"(b), "r"(c)); return r; }
__device__ __forceinline__ float rbf(float x) { uint32_t r; asm("cvt.rn.bf16x2.f32 %0, %1, %2;" : "=r"(r) : "f"(x), "f"(0.0f)); return __uint_as_float(r); }
__device__ __forceinline__ void stmatrix4(uint32_t a, uint32_t r0, uint32_t r1, uint32_t r2, uint32_t r3) {
  asm volatile("stmatrix.sync.aligned.m8n8.x4.shared.b16 [%0], {%1,%2,%3,%4};" ::"r"(a), "r"(r0), "r"(r1), "r"(r2), "r"(r3) : "memory");
}
__device__ __forceinline__ void stmatrix2(uint32_t a, uint32_t r0, uint32_t r1) {
  asm volatile("stmatrix.sync.aligned.m8n8.x2.shared.b16 [%0], {%1,%2};" ::"r"(a), "r"(r0), "r"(r1) : "memory");
}
__device__ __forceinline__ void stmatrix4t(uint32_t a, uint32_t r0, uint32_t r1, uint32_t r2, uint32_t r3) {
  asm volatile("stmatrix.sync.aligned.m8n8.x4.trans.shared.b16 [%0], {%1,%2,%3,%4};" ::"r"(a), "r"(r0), "r"(r1), "r"(r2), "r"(r3) : "memory");
}
__device__ __forceinline__ uint32_t movm(uint32_t a) { uint32_t r; asm("movmatrix.sync.aligned.m8n8.trans.b16 %0, %1;" : "=r"(r) : "r"(a)); return r; }
template <bool ACC> __device__ __forceinline__ void mma16(float* d, uint32_t a0, uint32_t a1, uint32_t a2, uint32_t a3, uint32_t b0, uint32_t b1) {
  if (ACC) asm("mma.sync.aligned.m16n8k16.row.col.f32.bf16.bf16.f32 {%0,%1,%2,%3}, {%4,%5,%6,%7}, {%8,%9}, {%0,%1,%2,%3};"
               : "+f"(d[0]), "+f"(d[1]), "+f"(d[2]), "+f"(d[3]) : "r"(a0), "r"(a1), "r"(a2), "r"(a3), "r"(b0), "r"(b1));
  else asm("mma.sync.aligned.m16n8k16.row.col.f32.bf16.bf16.f32 {%0,%1,%2,%3}, {%4,%5,%6,%7}, {%8,%9}, {%10,%10,%10,%10};"
           : "=f"(d[0]), "=f"(d[1]), "=f"(d[2]), "=f"(d[3]) : "r"(a0), "r"(a1), "r"(a2), "r"(a3), "r"(b0), "r"(b1), "f"(0.f));
}
__device__ __forceinline__ uint32_t pin(uint32_t v) { uint32_t r; asm volatile("shfl.sync.bfly.b32 %0, %1, 0, 31, 0xffffffff;" : "=r"(r) : "r"(v)); return r; }
__device__ __forceinline__ uint32_t set_tag(uint32_t w, uint32_t tag) { uint32_t r; asm("lop3.b32 %0, %1, 0xfffffffe, %2, 0xea;" : "=r"(r) : "r"(w), "r"(tag)); return r; }
__device__ __forceinline__ uint32_t diff2(uint32_t a, uint32_t b, uint32_t tag) { uint32_t r; asm("lop3.b32 %0, %1, %2, %3, 0x7e;" : "=r"(r) : "r"(a), "r"(b), "r"(tag)); return r; }
__device__ __forceinline__ float2 cmul(float2 a, float2 b) { return make_float2(a.x * b.x - a.y * b.y, a.x * b.y + a.y * b.x); }

template<int TB> __device__ __forceinline__ void wgmma_ss_160_0(float (&d)[80], uint32_t al, uint32_t ah, uint32_t bl, uint32_t bh) {
  asm volatile("{\n.reg .b64 da, db;\nmov.b64 da, {%80, %81};\nmov.b64 db, {%82, %83};\n"
    "wgmma.mma_async.sync.aligned.m64n160k16.f32.bf16.bf16 {%0,%1,%2,%3,%4,%5,%6,%7,%8,%9,%10,%11,%12,%13,%14,%15,%16,%17,%18,%19,%20,%21,%22,%23,%24,%25,%26,%27,%28,%29,%30,%31,%32,%33,%34,%35,%36,%37,%38,%39,%40,%41,%42,%43,%44,%45,%46,%47,%48,%49,%50,%51,%52,%53,%54,%55,%56,%57,%58,%59,%60,%61,%62,%63,%64,%65,%66,%67,%68,%69,%70,%71,%72,%73,%74,%75,%76,%77,%78,%79}, da, db, 1, 1, 1, 1, %84;\n}\n"
    : "+f"(d[0]),"+f"(d[1]),"+f"(d[2]),"+f"(d[3]),"+f"(d[4]),"+f"(d[5]),"+f"(d[6]),"+f"(d[7]),"+f"(d[8]),"+f"(d[9]),"+f"(d[10]),"+f"(d[11]),"+f"(d[12]),"+f"(d[13]),"+f"(d[14]),"+f"(d[15]),"+f"(d[16]),"+f"(d[17]),"+f"(d[18]),"+f"(d[19]),"+f"(d[20]),"+f"(d[21]),"+f"(d[22]),"+f"(d[23]),"+f"(d[24]),"+f"(d[25]),"+f"(d[26]),"+f"(d[27]),"+f"(d[28]),"+f"(d[29]),"+f"(d[30]),"+f"(d[31]),"+f"(d[32]),"+f"(d[33]),"+f"(d[34]),"+f"(d[35]),"+f"(d[36]),"+f"(d[37]),"+f"(d[38]),"+f"(d[39]),"+f"(d[40]),"+f"(d[41]),"+f"(d[42]),"+f"(d[43]),"+f"(d[44]),"+f"(d[45]),"+f"(d[46]),"+f"(d[47]),"+f"(d[48]),"+f"(d[49]),"+f"(d[50]),"+f"(d[51]),"+f"(d[52]),"+f"(d[53]),"+f"(d[54]),"+f"(d[55]),"+f"(d[56]),"+f"(d[57]),"+f"(d[58]),"+f"(d[59]),"+f"(d[60]),"+f"(d[61]),"+f"(d[62]),"+f"(d[63]),"+f"(d[64]),"+f"(d[65]),"+f"(d[66]),"+f"(d[67]),"+f"(d[68]),"+f"(d[69]),"+f"(d[70]),"+f"(d[71]),"+f"(d[72]),"+f"(d[73]),"+f"(d[74]),"+f"(d[75]),"+f"(d[76]),"+f"(d[77]),"+f"(d[78]),"+f"(d[79])
    : "r"(al), "r"(ah), "r"(bl), "r"(bh), "n"(TB));
}
template<int TB> __device__ __forceinline__ void wgmma_ss_144_0(float (&d)[80], uint32_t al, uint32_t ah, uint32_t bl, uint32_t bh) {
  asm volatile("{\n.reg .b64 da, db;\nmov.b64 da, {%72, %73};\nmov.b64 db, {%74, %75};\n"
    "wgmma.mma_async.sync.aligned.m64n144k16.f32.bf16.bf16 {%0,%1,%2,%3,%4,%5,%6,%7,%8,%9,%10,%11,%12,%13,%14,%15,%16,%17,%18,%19,%20,%21,%22,%23,%24,%25,%26,%27,%28,%29,%30,%31,%32,%33,%34,%35,%36,%37,%38,%39,%40,%41,%42,%43,%44,%45,%46,%47,%48,%49,%50,%51,%52,%53,%54,%55,%56,%57,%58,%59,%60,%61,%62,%63,%64,%65,%66,%67,%68,%69,%70,%71}, da, db, 1, 1, 1, 1, %76;\n}\n"
    : "+f"(d[0]),"+f"(d[1]),"+f"(d[2]),"+f"(d[3]),"+f"(d[4]),"+f"(d[5]),"+f"(d[6]),"+f"(d[7]),"+f"(d[8]),"+f"(d[9]),"+f"(d[10]),"+f"(d[11]),"+f"(d[12]),"+f"(d[13]),"+f"(d[14]),"+f"(d[15]),"+f"(d[16]),"+f"(d[17]),"+f"(d[18]),"+f"(d[19]),"+f"(d[20]),"+f"(d[21]),"+f"(d[22]),"+f"(d[23]),"+f"(d[24]),"+f"(d[25]),"+f"(d[26]),"+f"(d[27]),"+f"(d[28]),"+f"(d[29]),"+f"(d[30]),"+f"(d[31]),"+f"(d[32]),"+f"(d[33]),"+f"(d[34]),"+f"(d[35]),"+f"(d[36]),"+f"(d[37]),"+f"(d[38]),"+f"(d[39]),"+f"(d[40]),"+f"(d[41]),"+f"(d[42]),"+f"(d[43]),"+f"(d[44]),"+f"(d[45]),"+f"(d[46]),"+f"(d[47]),"+f"(d[48]),"+f"(d[49]),"+f"(d[50]),"+f"(d[51]),"+f"(d[52]),"+f"(d[53]),"+f"(d[54]),"+f"(d[55]),"+f"(d[56]),"+f"(d[57]),"+f"(d[58]),"+f"(d[59]),"+f"(d[60]),"+f"(d[61]),"+f"(d[62]),"+f"(d[63]),"+f"(d[64]),"+f"(d[65]),"+f"(d[66]),"+f"(d[67]),"+f"(d[68]),"+f"(d[69]),"+f"(d[70]),"+f"(d[71])
    : "r"(al), "r"(ah), "r"(bl), "r"(bh), "n"(TB));
}
template<int TB> __device__ __forceinline__ void wgmma_ss_96_0(float (&d)[80], uint32_t al, uint32_t ah, uint32_t bl, uint32_t bh) {
  asm volatile("{\n.reg .b64 da, db;\nmov.b64 da, {%48, %49};\nmov.b64 db, {%50, %51};\n"
    "wgmma.mma_async.sync.aligned.m64n96k16.f32.bf16.bf16 {%0,%1,%2,%3,%4,%5,%6,%7,%8,%9,%10,%11,%12,%13,%14,%15,%16,%17,%18,%19,%20,%21,%22,%23,%24,%25,%26,%27,%28,%29,%30,%31,%32,%33,%34,%35,%36,%37,%38,%39,%40,%41,%42,%43,%44,%45,%46,%47}, da, db, 1, 1, 1, 1, %52;\n}\n"
    : "+f"(d[0]),"+f"(d[1]),"+f"(d[2]),"+f"(d[3]),"+f"(d[4]),"+f"(d[5]),"+f"(d[6]),"+f"(d[7]),"+f"(d[8]),"+f"(d[9]),"+f"(d[10]),"+f"(d[11]),"+f"(d[12]),"+f"(d[13]),"+f"(d[14]),"+f"(d[15]),"+f"(d[16]),"+f"(d[17]),"+f"(d[18]),"+f"(d[19]),"+f"(d[20]),"+f"(d[21]),"+f"(d[22]),"+f"(d[23]),"+f"(d[24]),"+f"(d[25]),"+f"(d[26]),"+f"(d[27]),"+f"(d[28]),"+f"(d[29]),"+f"(d[30]),"+f"(d[31]),"+f"(d[32]),"+f"(d[33]),"+f"(d[34]),"+f"(d[35]),"+f"(d[36]),"+f"(d[37]),"+f"(d[38]),"+f"(d[39]),"+f"(d[40]),"+f"(d[41]),"+f"(d[42]),"+f"(d[43]),"+f"(d[44]),"+f"(d[45]),"+f"(d[46]),"+f"(d[47])
    : "r"(al), "r"(ah), "r"(bl), "r"(bh), "n"(TB));
}
template<int TB> __device__ __forceinline__ void wgmma_ss_48_48(float (&d)[80], uint32_t al, uint32_t ah, uint32_t bl, uint32_t bh) {
  asm volatile("{\n.reg .b64 da, db;\nmov.b64 da, {%24, %25};\nmov.b64 db, {%26, %27};\n"
    "wgmma.mma_async.sync.aligned.m64n48k16.f32.bf16.bf16 {%0,%1,%2,%3,%4,%5,%6,%7,%8,%9,%10,%11,%12,%13,%14,%15,%16,%17,%18,%19,%20,%21,%22,%23}, da, db, 1, 1, 1, 1, %28;\n}\n"
    : "+f"(d[48]),"+f"(d[49]),"+f"(d[50]),"+f"(d[51]),"+f"(d[52]),"+f"(d[53]),"+f"(d[54]),"+f"(d[55]),"+f"(d[56]),"+f"(d[57]),"+f"(d[58]),"+f"(d[59]),"+f"(d[60]),"+f"(d[61]),"+f"(d[62]),"+f"(d[63]),"+f"(d[64]),"+f"(d[65]),"+f"(d[66]),"+f"(d[67]),"+f"(d[68]),"+f"(d[69]),"+f"(d[70]),"+f"(d[71])
    : "r"(al), "r"(ah), "r"(bl), "r"(bh), "n"(TB));
}
__device__ __forceinline__ void wgmma_rs_72(float (&d)[36], uint32_t a0, uint32_t a1, uint32_t a2, uint32_t a3, uint32_t bl, uint32_t bh, int sd) {
  asm volatile("{\n.reg .pred p;\n.reg .b64 db;\nsetp.ne.b32 p, %42, 0;\nmov.b64 db, {%40, %41};\n"
    "wgmma.mma_async.sync.aligned.m64n72k16.f32.bf16.bf16 {%0,%1,%2,%3,%4,%5,%6,%7,%8,%9,%10,%11,%12,%13,%14,%15,%16,%17,%18,%19,%20,%21,%22,%23,%24,%25,%26,%27,%28,%29,%30,%31,%32,%33,%34,%35}, {%36,%37,%38,%39}, db, p, 1, 1, 1;\n}\n"
    : "+f"(d[0]),"+f"(d[1]),"+f"(d[2]),"+f"(d[3]),"+f"(d[4]),"+f"(d[5]),"+f"(d[6]),"+f"(d[7]),"+f"(d[8]),"+f"(d[9]),"+f"(d[10]),"+f"(d[11]),"+f"(d[12]),"+f"(d[13]),"+f"(d[14]),"+f"(d[15]),"+f"(d[16]),"+f"(d[17]),"+f"(d[18]),"+f"(d[19]),"+f"(d[20]),"+f"(d[21]),"+f"(d[22]),"+f"(d[23]),"+f"(d[24]),"+f"(d[25]),"+f"(d[26]),"+f"(d[27]),"+f"(d[28]),"+f"(d[29]),"+f"(d[30]),"+f"(d[31]),"+f"(d[32]),"+f"(d[33]),"+f"(d[34]),"+f"(d[35])
    : "r"(a0), "r"(a1), "r"(a2), "r"(a3), "r"(bl), "r"(bh), "r"(sd));
}
__device__ __forceinline__ void wgmma_rs_48(float (&d)[24], uint32_t a0, uint32_t a1, uint32_t a2, uint32_t a3, uint32_t bl, uint32_t bh, int sd) {
  asm volatile("{\n.reg .pred p;\n.reg .b64 db;\nsetp.ne.b32 p, %30, 0;\nmov.b64 db, {%28, %29};\n"
    "wgmma.mma_async.sync.aligned.m64n48k16.f32.bf16.bf16 {%0,%1,%2,%3,%4,%5,%6,%7,%8,%9,%10,%11,%12,%13,%14,%15,%16,%17,%18,%19,%20,%21,%22,%23}, {%24,%25,%26,%27}, db, p, 1, 1, 1;\n}\n"
    : "+f"(d[0]),"+f"(d[1]),"+f"(d[2]),"+f"(d[3]),"+f"(d[4]),"+f"(d[5]),"+f"(d[6]),"+f"(d[7]),"+f"(d[8]),"+f"(d[9]),"+f"(d[10]),"+f"(d[11]),"+f"(d[12]),"+f"(d[13]),"+f"(d[14]),"+f"(d[15]),"+f"(d[16]),"+f"(d[17]),"+f"(d[18]),"+f"(d[19]),"+f"(d[20]),"+f"(d[21]),"+f"(d[22]),"+f"(d[23])
    : "r"(a0), "r"(a1), "r"(a2), "r"(a3), "r"(bl), "r"(bh), "r"(sd));
}
template<int N,int OFF,int TB> __device__ __forceinline__ void wgmma_ss(float (&d)[80], uint32_t al, uint32_t ah, uint32_t bl, uint32_t bh) {
  if constexpr (N==160) wgmma_ss_160_0<TB>(d, al, ah, bl, bh);
  else if constexpr (N==144) wgmma_ss_144_0<TB>(d, al, ah, bl, bh);
  else if constexpr (N==96) wgmma_ss_96_0<TB>(d, al, ah, bl, bh);
  else if constexpr (N==48) wgmma_ss_48_48<TB>(d, al, ah, bl, bh);
}

__device__ __forceinline__ void dft3(float2& a, float2& b, float2& c) {
  const float s = 0.86602540378443864676f;
  float2 t = make_float2(b.x + c.x, b.y + c.y), d = make_float2(b.x - c.x, b.y - c.y);
  float2 m = make_float2(fmaf(-0.5f, t.x, a.x), fmaf(-0.5f, t.y, a.y));
  a = make_float2(a.x + t.x, a.y + t.y);
  b = make_float2(fmaf(s, d.y, m.x), fmaf(-s, d.x, m.y));
  c = make_float2(fmaf(-s, d.y, m.x), fmaf(s, d.x, m.y));
}
__device__ __forceinline__ void dft9(float2 (&x)[9]) {
  const float2 w1 = make_float2(0.76604444311897803520f, -0.64278760968653932632f);
  const float2 w2 = make_float2(0.17364817766693034885f, -0.98480775301220805937f);
  const float2 w4 = make_float2(-0.93969262078590838405f, -0.34202014332566873304f);
  dft3(x[0], x[3], x[6]); dft3(x[1], x[4], x[7]); dft3(x[2], x[5], x[8]);
  x[4] = cmul(x[4], w1); x[7] = cmul(x[7], w2); x[5] = cmul(x[5], w2); x[8] = cmul(x[8], w4);
  dft3(x[0], x[1], x[2]); dft3(x[3], x[4], x[5]); dft3(x[6], x[7], x[8]);
  float2 t;
  t = x[1]; x[1] = x[3]; x[3] = t;
  t = x[2]; x[2] = x[6]; x[6] = t;
  t = x[5]; x[5] = x[7]; x[7] = t;
}

__device__ __forceinline__ void mod_fma(float (&acc)[8], float sc, const uint4& w) {
  acc[0] = fmaf(sc, bf_lo(w.x), acc[0]); acc[1] = fmaf(sc, bf_hi(w.x), acc[1]);
  acc[2] = fmaf(sc, bf_lo(w.y), acc[2]); acc[3] = fmaf(sc, bf_hi(w.y), acc[3]);
  acc[4] = fmaf(sc, bf_lo(w.z), acc[4]); acc[5] = fmaf(sc, bf_hi(w.z), acc[5]);
  acc[6] = fmaf(sc, bf_lo(w.w), acc[6]); acc[7] = fmaf(sc, bf_hi(w.w), acc[7]);
}
__device__ __forceinline__ void mod_finish(const Params& p, float (&acc)[8], int u, int t128, uint32_t red, uint32_t tag) {
#pragma unroll
  for (int n = 4, o = 2; n; n >>= 1, o <<= 1) {
    const bool up = t128 & o;
#pragma unroll
    for (int e = 0; e < n; e++) acc[e] = (up ? acc[e + n] : acc[e]) + __shfl_xor_sync(0xffffffffu, up ? acc[e] : acc[e + n], o);
  }
  acc[0] += __shfl_xor_sync(0xffffffffu, acc[0], 16);
  const int col = 8 * (t128 & 1) + 2 * (t128 & 2) + ((t128 >> 1) & 2) + ((t128 >> 3) & 1);
  if (!(t128 & 16)) sts(red + (col * 4 + (t128 >> 5)) * 4, __float_as_uint(acc[0]));
  bar_sync(4, 128);
  if (t128 < 16) {
    const uint4 v = lds4(red + t128 * 16);
    float m = rbf((__uint_as_float(v.x) + __uint_as_float(v.y)) + (__uint_as_float(v.z) + __uint_as_float(v.w)));
    const int kind = u / 36;
    if (kind == 0) m *= 16.0f;
    if (kind == 1 || kind == 4) m = rbf(1.0f + m);
    p.s->mod[16 * u + (kind < 2 ? 2 * (t128 & 7) + (t128 >> 3) : t128)] = __float_as_uint(m) | tag;
  }
}

__device__ __forceinline__ void ln_stats2(const float (&a)[18], const float (&b)[18], float sc, float& oa, float& ra, float& ob, float& rb) {
  float v[4] = {0.f, 0.f, 0.f, 0.f}, w[4] = {0.f, 0.f, 0.f, 0.f};
#pragma unroll
  for (int i = 0; i < 18; i += 2) {
    v[0] += a[i]; v[1] = fmaf(a[i], a[i], v[1]); v[2] += b[i]; v[3] = fmaf(b[i], b[i], v[3]);
    w[0] += a[i + 1]; w[1] = fmaf(a[i + 1], a[i + 1], w[1]); w[2] += b[i + 1]; w[3] = fmaf(b[i + 1], b[i + 1], w[3]);
  }
#pragma unroll
  for (int e = 0; e < 4; e++) v[e] += w[e];
#pragma unroll
  for (int o = 16; o; o >>= 1) {
#pragma unroll
    for (int e = 0; e < 4; e++) v[e] += __shfl_xor_sync(0xffffffffu, v[e], o);
  }
  const float ma = v[0] * (1.0f / D_), mb = v[2] * (1.0f / D_);
  ra = sc * rsqrtf(fmaxf(fmaf(-ma, ma, v[1] * (1.0f / D_)), 0.f) + 1e-5f);
  rb = sc * rsqrtf(fmaxf(fmaf(-mb, mb, v[3] * (1.0f / D_)), 0.f) + 1e-5f);
  oa = -ma * ra; ob = -mb * rb;
}

__device__ __forceinline__ float tmat(int c, int q, int j) {
  const int ph = q == 1 ? 1024 * j : (q >> 1) * (c + 128 * j) + 512 * (q & 1);
  return __cosf((float)(((ph + 1024) & 2047) - 1024) * (6.283185307179586f / 2048.0f));
}
__device__ __forceinline__ uint32_t line_off(int k1, int kap, int pi, int f) {
  int kd = 64 * k1 + 9 * kap;
  if (kap == 0 && k1 > 4) kd -= 288;
  if (kd >= D_) kd -= D_;
  return pi * 2400 + ((min(kd, D_ - kd) ^ f) << 3);
}

constexpr int JSK = 5;
struct Ring { uint32_t st, ph; };
template <bool G2, class T> __device__ __forceinline__ void ring_next(T& st, T& ph) {
  if (++st == NST) st = 0;
  ph ^= ((G2 ? 0xDu : 0x1u) >> st) & 1;
}
__device__ __forceinline__ uint32_t mapa(uint32_t a, uint32_t cta) { uint32_t r; asm("mapa.shared::cluster.u32 %0, %1, %2;" : "=r"(r) : "r"(a), "r"(cta)); return r; }
__device__ __forceinline__ void arrive_if(uint32_t a, uint32_t p) {
  asm volatile("{\n.reg .pred p;\nsetp.ne.u32 p, %1, 0;\n@p mbarrier.arrive.shared::cluster.b64 _, [%0];\n}" ::"r"(a), "r"(p) : "memory");
}
template <int NA> __device__ __forceinline__ void reg_fence_n(float (&d)[80]) {
#pragma unroll
  for (int i = 0; i < NA; i++) asm volatile("" : "+f"(d[i])::"memory");
}
template <int MODE>
__device__ __forceinline__ void gemm_main(float (&acc)[80], uint32_t da0, uint32_t da1, uint32_t db0, uint32_t db1, int wg, uint32_t rank,
                                          Ring& rg, uint32_t full0, uint32_t rdy) {
  static_assert(JSK == NST - 1, "the held slot is the first one that is not refilled by GEMM1");
  constexpr int NKB = MODE == 3 ? 36 : 32;
  constexpr uint32_t HA = 0x40000040u, HB = MODE == 3 ? 0x40000040u : 0x80000020u;
  constexpr uint32_t KA = 2048 >> 4, KB = MODE == 3 ? (32 >> 4) : (1024 >> 4);
  constexpr int NA = MODE ? 72 : 80;
  const uint32_t t = threadIdx.x & 127;
  const uint32_t eb = mapa(full0 + 8 * NST, rank);
  uint32_t pb = 0, rel = t == 0, prel = 0;
  int n = NKB - JSK;
#pragma unroll 1
  for (int pass = 0;; pass++) {
#pragma unroll 1
    do {
      const uint32_t so = rg.st * (STAGE >> 4);
      mbar_wait(full0 + 8 * rg.st, rg.ph);
      reg_fence_n<NA>(acc);
      wg_fence();
#pragma unroll
      for (int k = 0; k < 4; k++) {
        if (MODE == 0) wgmma_ss<160, 0, 1>(acc, da0 + so + k * KA, HA, db0 + so + k * KB, HB);
        else if (MODE == 3) wgmma_ss<144, 0, 0>(acc, da0 + so + k * KA, HA, db0 + so + k * KB, HB);
        else {
          wgmma_ss<96, 0, 1>(acc, da0 + so + k * KA, HA, db0 + so + k * KB, HB);
          wgmma_ss<48, 48, 1>(acc, da1 + so + k * KA, HA, db1 + so + k * KB, HB);
        }
      }
      wg_commit();
      wg_wait<1>();
      reg_fence_n<NA>(acc);
      arrive_if(pb, prel);
      pb = eb + 8 * rg.st; prel = rel;
      ring_next<MODE == 3>(rg.st, rg.ph);
    } while (--n);
    if (pass == 2 - wg) break;
    n = 1;
    if (pass == 0) {
      if (MODE != 3) prel = rel & wg;
      else { if (t == 1) pb = mapa(rdy, rank ^ 1); prel = t < 2; rel = 0; }
      n = JSK - 1 + wg;
      if (!wg) continue;
      wg_wait<0>();
      arrive_if(pb, prel);
      prel = 0;
    }
    bar_sync(1, 256);
  }
  wg_wait<0>();
  reg_fence_n<NA>(acc);
  if (MODE != 3) arrive_if(pb, prel & ~wg);
}

__device__ __forceinline__ float gelu_arg(float h) { return h * fmaf(8.0f * 0.044715f * 0.7978845608028654f, h * h, 2.0f * 0.7978845608028654f); }

__device__ __forceinline__ int kb2_order(int i) { const int wv = i / 6; return 6 * (i - 6 * wv) + ((0x431250 >> (4 * wv)) & 7); }

__device__ __forceinline__ void wait_flags(const unsigned* base, int n, int idx, unsigned target, uint64_t& ready) {
  if ((ready >> idx) & 1) return;
  const int l = threadIdx.x & 31;
  int it = 0;
  while (true) {
    unsigned a = ld_rlx(base + l), b = l + 32 < n ? ld_rlx(base + l + 32) : target;
    ready = (uint64_t)__ballot_sync(0xffffffffu, (int)(a - target) >= 0) | ((uint64_t)__ballot_sync(0xffffffffu, (int)(b - target) >= 0) << 32);
    if (((ready >> idx) & 1) || ++it > SPIN_MAX) break;
  }
  fence_async_glb();
}

enum { B_FULL = 0, B_EMPTY = 6, B_FLT = 12, B_Z1, B_Z2, B_RDY, B_RCV, B_GO, B_S4, B_S5, B_WM, B_NUM, B_W0 = B_NUM };

__global__ void __launch_bounds__(NTHR, 1)
fused_kernel(const Params p, const __grid_constant__ Maps maps) {
  extern __shared__ uint8_t smem_raw[];
  __shared__ uint64_t bars[B_NUM + 1];
  __shared__ __align__(16) float redbuf[128 + D_];

  const uint32_t sbase = (smem_u32(smem_raw) + 1023) & ~1023u;
  const uint32_t full0 = smem_u32(bars), empty0 = full0 + 8 * B_EMPTY, red = smem_u32(redbuf);
  const int tid = threadIdx.x, cta = blockIdx.x, t128 = tid & 127;
  const int wp = __shfl_sync(0xffffffffu, tid >> 5, 0), wg = wp >> 2;
  const int l = tid & 31, g = l >> 2, t = l & 3;
  const int q = cta >> 1, r = cta & 1;
  Scratch* const sc = p.s;
  const bool rows = cta < 128;
  const int R = cta - 12;

  uint32_t xr[18];
  uint32_t cv[9];
  const unsigned ep = ld_rlx(&sc->cnt[C_EP]) + 1;
  if (tid == 0) TS(0);
  if (wg == 2) {
#pragma unroll
    for (int i = 0; i < 9; i++) asm volatile("ld.global.nc.u16 %0, [%1];" : "=r"(cv[i]) : "l"(p.c + (t128 >> 1) + 64 * i) : "memory");
    if (wp == 9 && l < 9 && rows) {
      const int h = 9 * cta + l;
      prefetch_l2(reinterpret_cast<const uint8_t*>(p.wmod) + (size_t)(h >> 1) * (12 * D_) + (h & 1) * (2 * D_), 2 * D_);
    }
    if (tid == 256 && cta < 72) {
      mbar_init(full0 + 8 * B_W0, 1);
      fence_async_smem();
      mbar_expect(full0 + 8 * B_W0, 18432);
#pragma unroll 1
      for (int i = 0; i < 3; i++) tma2d(sbase + O_P2 + i * 6144, &maps.wm, 16 * cta, 192 * i, full0 + 8 * B_W0);
    }
    if (tid == 352) {
#pragma unroll 1
      for (int i = 0; i < B_NUM; i++) mbar_init(full0 + 8 * i, i == B_FLT ? 4 : i == B_WM ? 3 : (i >= B_EMPTY && i < B_FLT) || i == B_RDY ? 2 : 1);
      mbar_expect(full0 + 8 * B_RCV, 18432);
      asm volatile("fence.mbarrier_init.release.cluster;" ::: "memory");
      fence_async_smem();
    }
    if (wp == 10 && l < 10) asm volatile("prefetch.tensormap [%0];" ::"l"(&maps.w1a + l) : "memory");
    __syncwarp();
  }
  CK(0);
  auto load_x = [&]() {
    const uint32_t* xs = reinterpret_cast<const uint32_t*>(p.x) + (size_t)(cta + 256 * wp) * 288 + l;
#pragma unroll
    for (int i = 0; i < 9; i++) { xr[i] = ld_nc(xs + 32 * i); xr[9 + i] = ld_nc(xs + 128 * 288 + 32 * i); }
  };
  if (tid == 64 && cta == NCTA - 1) prefetch_l2(p.tab, sizeof(T_TAB));
  __syncwarp();
  asm volatile("barrier.cluster.arrive.relaxed.aligned;" ::: "memory");
  int gq, gi;
  {
    const int tq = q - 4;
    gq = q < 4 ? 0 : tq < 32 ? (tq & 7) : tq < 60 ? 1 + (tq - 32) % 7 : tq - 54;
    gi = q < 4 ? q : tq < 32 ? (tq >> 3) + (gq == 0 ? 4 : 0) : tq < 60 ? 4 + (tq - 32) / 7 : 8;
  }
  const int j1 = 2 * (8 * gq + (gq == 7) + gi) + r;
  const int role = j1 % 11 + 16 * (j1 / 11) + 256 * (8 * gq + gi);
  const uint32_t tag16 = ep & 0xffffu, tag1 = ep & 1u;

  if (wg == 2) {
    float sil[9];
#pragma unroll
    for (int i = 0; i < 9; i++) sil[i] = rbf(__fdividef(bf_lo(cv[i]), 1.0f + __expf(-bf_lo(cv[i]))));
    if (cta < 72) {
      float acc[8] = {0.f, 0.f, 0.f, 0.f, 0.f, 0.f, 0.f, 0.f};
      bar_sync(4, 128);
      mbar_wait(full0 + 8 * B_W0, 0);
#pragma unroll
      for (int i = 0; i < 9; i++) mod_fma(acc, sil[i], lds4(sbase + O_P2 + t128 * 16 + i * 2048));
      mod_finish(p, acc, cta, t128, red, tag16);
      if (t128 == 0) TS(25);
    }
#pragma unroll
    for (int i = 0; i < 9; i++) sts(red + 512 + ((t128 >> 1) + 64 * i) * 4, __float_as_uint(sil[i]));
    CK(1);
  }
  const int pi = R / 15, col0 = 20 * (R - 15 * pi);
  const int xu = DF_ * pi + col0, xv = DF_ * (pi ? 16 - pi : 8) + col0;
  auto load_filter = [&]() {
    if (R >= 0 && l == 0) {
      mbar_expect(full0 + 8 * B_FLT, 10240);
      tma2d(sbase + O_RAW + (wp - 8) * 10240, (wp & 2) ? &maps.wi : &maps.wr, ((wp & 1) ? xv : xu) & ~7, 0, full0 + 8 * B_FLT);
    }
    __syncwarp();
  };
  const int kap = 8 * ((wp & 3) ^ (wg & 1)) + g;
  uint4 af[4];
  if (rows) {
    uint32_t tb[4];
#pragma unroll
    for (int i = 0; i < 4; i++) tb[i] = pack_bf16(tmat(cta, 8 * (i >> 1) + g, 2 * t + 8 * (i & 1)), tmat(cta, 8 * (i >> 1) + g, 2 * t + 8 * (i & 1) + 1));
    uint32_t sb1[3], lo[9];
#pragma unroll
    for (int i = 0; i < 4; i++) tb[i] = pin(tb[i]);
    if (wg < 2) load_x();
#pragma unroll
    for (int i = 0; i < 3; i++) {
      const int d = 48 * wp + 16 * i + (l & 15);
      sb1[i] = pin(sbase + O_B1 + (l >> 4) * 9216 + (d % 9) * 1024 + (d & 63) * 16);
    }
    const uint32_t snt = pin(sbase + O_NRM + ((l & 7) + 8 * (l >> 4)) * 1168 + (48 * wp + (l & 8)) * 2);
    if (wg < 2) {
#pragma unroll
      for (int k1 = 0; k1 < 9; k1++) lo[k1] = pin(sbase + O_Z1 + line_off(k1, kap, 4 * wg + t, cta & 3));
#pragma unroll
      for (int kk = 0; kk < 4; kk++) af[kk] = __ldg(p.tab + TB_F + kk * 128 + (t128 ^ (wg << 5)));
      float a[18], b[18];
#pragma unroll
      for (int i = 0; i < 9; i++) { a[2 * i] = bf_lo(xr[i]); a[2 * i + 1] = bf_hi(xr[i]); b[2 * i] = bf_lo(xr[9 + i]); b[2 * i + 1] = bf_hi(xr[9 + i]); }
      float oa, ra, ob, rb;
      ln_stats2(a, b, 1.0f, oa, ra, ob, rb);
      CK(1);
      const uint32_t sn = sbase + O_NRM + wp * 2336 + l * 4;
#pragma unroll
      for (int i = 0; i < 9; i++) {
        sts(sn + i * 128, pack_bf16(fmaf(a[2 * i], ra, oa), fmaf(a[2 * i + 1], ra, oa)));
        sts(sn + 1168 + i * 128, pack_bf16(fmaf(b[2 * i], rb, ob), fmaf(b[2 * i + 1], rb, ob)));
      }
      CK(2);
      bar_arrive(10, NTHR);
      bar_sync(1, 256);
      if (tid == 0) TS(2);
    } else {
      bar_sync(10, NTHR);
      CK(2);
      load_filter();
    }
    float rs[3][8];
#pragma unroll
    for (int i = 0; i < 3; i++) {
      uint32_t a0, a1, a2, a3;
      asm volatile("ldmatrix.sync.aligned.m8n8.x4.trans.shared.b16 {%0,%1,%2,%3}, [%4];" : "=r"(a0), "=r"(a1), "=r"(a2), "=r"(a3)
                   : "r"(snt + 32 * i) : "memory");
      mma16<false>(&rs[i][0], a0, a1, a2, a3, tb[0], tb[1]);
      mma16<false>(&rs[i][4], a0, a1, a2, a3, tb[2], tb[3]);
    }
    CK(3);
    {
      uint2 ms[3], mc[3];
      const uint32_t* mp = sc->mod + 48 * wp + 2 * g;
      int it = 0;
#pragma unroll 1
      while (true) {
        uint32_t bad = 0;
#pragma unroll
        for (int i = 0; i < 3; i++) { ms[i] = ld_rlx2(mp + 16 * i); mc[i] = ld_rlx2(mp + D_ + 16 * i); }
#pragma unroll
        for (int i = 0; i < 3; i++) {
          ms[i].x ^= tag16; ms[i].y ^= tag16; mc[i].x ^= tag16; mc[i].y ^= tag16;
          bad |= ms[i].x | ms[i].y | mc[i].x | mc[i].y;
        }
        if (!any(bad & 0xffffu) || ++it > SPIN_MAX) break;
      }
      CK(4);
      if (tid == 0) TS(3);
#pragma unroll
      for (int i = 0; i < 3; i++) {
        const float c0 = __uint_as_float(mc[i].x), c1 = __uint_as_float(mc[i].y);
        const float s0 = t ? 0.f : __uint_as_float(ms[i].x), s1 = t ? 0.f : __uint_as_float(ms[i].y);
        stmatrix4(sb1[i], pack_bf16(fmaf(rs[i][0], c0, s0), rs[i][1] * c0), pack_bf16(fmaf(rs[i][2], c1, s1), rs[i][3] * c1),
                  pack_bf16(rs[i][4] * c0, rs[i][5] * c0), pack_bf16(rs[i][6] * c1, rs[i][7] * c1));
      }
    }
    fence_async_smem();
    CK(5);
    if (wg == 2) bar_arrive(5, NTHR);
    else {
      bar_sync(5, NTHR);
      CK(6);
      float acc[36];
      const uint32_t db = (((sbase + O_B1 + wg * 9216) & 0x3FFFF) >> 4) | ((128 >> 4) << 16);
      wg_fence();
#pragma unroll
      for (int kk = 0; kk < 4; kk++) wgmma_rs_72(acc, af[kk].x, af[kk].y, af[kk].z, af[kk].w, db + kk * 16, 1024 >> 4, kk);
      wg_commit();
      wg_wait<0>();
      reg_fence(acc);
      CK(7);
      float2 za[9], zb[9];
#pragma unroll
      for (int i = 0; i < 9; i++) { za[i] = make_float2(acc[4 * i], acc[4 * i + 2]); zb[i] = make_float2(acc[4 * i + 1], acc[4 * i + 3]); }
      dft9(za); dft9(zb);
      if (kap == 0) {
#pragma unroll
        for (int k = 1; k < 5; k++) {
          float2 a = za[k], b = za[9 - k];
          za[k] = make_float2(a.x + b.x, a.y - b.y); za[9 - k] = make_float2(a.y + b.y, b.x - a.x);
          a = zb[k]; b = zb[9 - k];
          zb[k] = make_float2(a.x + b.x, a.y - b.y); zb[9 - k] = make_float2(a.y + b.y, b.x - a.x);
        }
        sts2(lo[0] + 288 * 8, set_tag(pack_bf16(za[0].y, 0.f), tag1), pack_bf16(zb[0].y, 0.f));
        za[0].y = 0.f; zb[0].y = 0.f;
      }
      __syncwarp();
#pragma unroll
      for (int k1 = 0; k1 < 9; k1++) sts2(lo[k1], set_tag(pack_bf16(za[k1].x, za[k1].y), tag1), pack_bf16(zb[k1].x, zb[k1].y));
      fence_async_smem();
      CK(8);
      bar_arrive(2 + wg, 160);
    }
  } else {
    __syncthreads();
    if (wg == 2) load_filter();
  }

  auto publish_z1 = [&]() {
    if (rows && (wp >> 1) == 4) {
      bar_sync(wp - 6, 160);
      if (l == 0) {
        const int slot = 4 * (cta & 7) + ((cta >> 4) & 3) + 32 * (2 * (cta >> 6) + ((cta >> 3) & 1));
        tma_st2d(&maps.z1, sbase + O_Z1 + (wp - 8) * 9600, 40 * slot, 60 * (wp - 8));
        bulk_commit_wait_read();
        red_add(&sc->cnt[C_Z1 + 32 * (wp - 8)], 1);
        if (wp == 8) TS(4);
      }
      __syncwarp();
    }
  };
  auto load_wm = [&](int u) {
    if (wp > 8 && l == 0) {
      mbar_expect(full0 + 8 * B_WM, 6144);
      tma2d(sbase + O_NRM + (wp - 9) * 6144, &maps.wm, 16 * u, 192 * (wp - 9), full0 + 8 * B_WM);
    }
    __syncwarp();
  };
  if (R < 0) publish_z1();
  if (R >= 0) {
    const int ln0 = wg < 2 ? 2 * wp : 8 + wp;
    const int nl = min(wg < 2 ? 2 : 1, DF_ - col0 - ln0);
    uint4 cf[2][4], G[4];
#pragma unroll
    for (int i = 0; i < 4; i++) {
      cf[0][i] = __ldg(p.tab + TB_P2 + i * 32 + l);
      cf[1][i] = __ldg(p.tab + TB_P2 + (pi ? i : 4 + i) * 32 + l);
      G[i] = __ldg(p.tab + TB_P2 + (8 + i) * 32 + l);
    }
    const uint32_t scf = sbase + O_CF + ln0 * 3072 + l * 16;
    mbar_wait(full0 + 8 * B_FLT, 0);
    CK(9);
#pragma unroll 1
    for (int ln = 0; ln < nl; ln++) {
      const int col = col0 + ln0 + ln, k2 = (57 * col) & 63;
      const bool cj = k2 > 32 || (k2 == 32 && col != 288);
      const float nr = ((col & 31) == 0 && col != 0 && col != 288 ? 0.5f : 1.0f) / ((float)S_ * D_), ni = cj ? -nr : nr;
      const float al = pi ? 1.0f : 0.0f, sq = cj ? -al : al;
      const uint32_t su = sbase + O_RAW + ((xu & 7) + ln0 + ln) * 2, sv = sbase + O_RAW + 10240 + ((xv & 7) + ln0 + ln) * 2;
      float o[24];
#pragma unroll
      for (int tt = 0; tt < 4; tt++) {
        const int kc = g + 64 * (tt >> 1) + 16 * t + 8 * (tt & 1);
        const int mu = (cj ? -kc : kc) & 127, mv = (cj ? -kc - 1 : kc - (pi != 0)) & 127;
        const float ur = lds_bf(su + mu * 80) * nr, ui = lds_bf(su + 20480 + mu * 80) * ni;
        const float vr = lds_bf(sv + mv * 80) * nr, vi = lds_bf(sv + 20480 + mv * 80) * ni;
        o[6 * tt] = fmaf(al, vr, ur); o[6 * tt + 1] = fmaf(al, vi, ui);
        o[6 * tt + 2] = sq * (vi - ui); o[6 * tt + 3] = sq * (ur - vr);
        o[6 * tt + 4] = fmaf(al, ur, vr); o[6 * tt + 5] = fmaf(al, ui, vi);
      }
#pragma unroll
      for (int i = 0; i < 6; i++)
        sts4(scf + ln * 3072 + i * 512, __float_as_uint(o[4 * i]), __float_as_uint(o[4 * i + 1]), __float_as_uint(o[4 * i + 2]), __float_as_uint(o[4 * i + 3]));
    }
    CK(10);
    const uint32_t* zin = sc->z1 + (size_t)R * 5120;
    uint32_t off = pin(l * 160 + ((ln0 ^ (g & 3)) << 3));
    publish_z1();
    if (wp == 10) {
      wait_cnt(&sc->cnt[C_Z1 + 32 * (pi >> 2)], 128 * ep);
      if (l == 0) {
        TS(12);
        mbar_expect(full0 + 8 * B_Z1, 20480);
        bulk_ld(sbase + O_P2, zin, 20480, full0 + 8 * B_Z1);
      }
      __syncwarp();
    }
    mbar_wait(full0 + 8 * B_Z1, 0);
    CK(11);
    if (tid == 0) TS(8);
    if (wg == 2) load_wm(72 + cta);
#pragma unroll 1
    for (int ln = 0; ln < nl; ln++, off ^= 8) {
      uint2 v[4];
#pragma unroll
      for (int i = 0; i < 4; i++) v[i] = lds2(sbase + O_P2 + off + i * 5120);
      if (__builtin_expect(any((diff2(v[0].x, v[1].x, tag1) | diff2(v[2].x, v[3].x, tag1)) & 1), 0)) {
        FAILCNT(0);
        int it = 0;
        do {
#pragma unroll
          for (int i = 0; i < 4; i++) v[i] = ld_rlx2(reinterpret_cast<const uint8_t*>(zin) + off + i * 5120);
        } while (any((diff2(v[0].x, v[1].x, tag1) | diff2(v[2].x, v[3].x, tag1)) & 1) && ++it < SPIN_MAX);
      }
      uint4 co[6];
#pragma unroll
      for (int i = 0; i < 6; i++) co[i] = lds4(scf + ln * 3072 + i * 512);
      float d[4][4];
      uint32_t A[8];
#pragma unroll
      for (int h = 0; h < 2; h++) {
        mma16<false>(d[2 * h], cf[0][0].x, cf[0][0].y, cf[0][0].z, cf[0][0].w, v[h].x, v[2 + h].x);
        mma16<false>(d[2 * h + 1], cf[1][0].x, cf[1][0].y, cf[1][0].z, cf[1][0].w, v[h].y, v[2 + h].y);
      }
#pragma unroll
      for (int h = 0; h < 2; h++)
#pragma unroll
        for (int L = 0; L < 2; L++) {
          const uint4 tw = cf[L][2 + h];
          const float* z = d[2 * h + L];
          const float2 z0 = cmul(make_float2(z[0], z[2]), make_float2(__uint_as_float(tw.x), __uint_as_float(tw.y)));
          const float2 z1 = cmul(make_float2(z[1], z[3]), make_float2(__uint_as_float(tw.z), __uint_as_float(tw.w)));
          A[4 * h + L] = pack_bf16(z0.x, z0.y); A[4 * h + 2 + L] = pack_bf16(z1.x, z1.y);
        }
#pragma unroll
      for (int tt = 0; tt < 4; tt++) {
        mma16<false>(d[tt], A[0], A[1], A[2], A[3], G[tt].x, G[tt].y);
        mma16<true>(d[tt], A[4], A[5], A[6], A[7], G[tt].z, G[tt].w);
      }
#pragma unroll
      for (int tt = 0; tt < 4; tt++) {
        const uint32_t* cw = reinterpret_cast<const uint32_t*>(co) + 6 * tt;
        const float pr = __uint_as_float(cw[0]), pj = __uint_as_float(cw[1]), qr = __uint_as_float(cw[2]), qj = __uint_as_float(cw[3]);
        const float rr = __uint_as_float(cw[4]), rj = __uint_as_float(cw[5]);
        const float ar = d[tt][0], aj = d[tt][1], br = d[tt][2], bj = d[tt][3];
        A[2 * tt] = pack_bf16(fmaf(-qj, bj, fmaf(qr, br, fmaf(-pj, aj, pr * ar))), fmaf(-qj, br, fmaf(-qr, bj, fmaf(-pj, ar, -pr * aj))));
        A[2 * tt + 1] = pack_bf16(fmaf(qj, aj, fmaf(-qr, ar, fmaf(-rj, bj, rr * br))), fmaf(qj, ar, fmaf(qr, aj, fmaf(-rj, br, -rr * bj))));
      }
#pragma unroll
      for (int tt = 0; tt < 4; tt++) {
        mma16<false>(d[tt], A[0], A[1], A[2], A[3], G[tt].x, G[tt].y);
        mma16<true>(d[tt], A[4], A[5], A[6], A[7], G[tt].z, G[tt].w);
      }
#pragma unroll
      for (int h = 0; h < 2; h++)
#pragma unroll
        for (int L = 0; L < 2; L++) {
          const uint4 tw = cf[L][2 + h];
          const float2 z0 = cmul(make_float2(d[2 * h][2 * L], d[2 * h][2 * L + 1]), make_float2(__uint_as_float(tw.x), __uint_as_float(tw.y)));
          const float2 z1 = cmul(make_float2(d[2 * h + 1][2 * L], d[2 * h + 1][2 * L + 1]), make_float2(__uint_as_float(tw.z), __uint_as_float(tw.w)));
          A[4 * h + 2 * L] = movm(pack_bf16(z0.x, z1.x)); A[4 * h + 2 * L + 1] = movm(pack_bf16(z0.y, z1.y));
        }
#pragma unroll
      for (int h = 0; h < 2; h++) {
        mma16<false>(d[0], cf[0][1].x, cf[0][1].y, cf[0][1].z, cf[0][1].w, A[4 * h], A[4 * h + 1]);
        mma16<false>(d[1], cf[1][1].x, cf[1][1].y, cf[1][1].z, cf[1][1].w, A[4 * h + 2], A[4 * h + 3]);
#pragma unroll
        for (int e = 0; e < 2; e++)
          sts2(sbase + O_P2 + off + (2 * h + e) * 5120, set_tag(pack_bf16(d[0][e], d[0][2 + e]), tag1), pack_bf16(d[1][e], d[1][2 + e]));
      }
      CK(12 + ln);
    }
    fence_async_smem();
    if (wp) bar_arrive(6, NTHR);
    else {
      bar_sync(6, NTHR);
      if (l == 0) {
        tma_st2d(&maps.z2, sbase + O_P2, 40 * R, 0);
        bulk_commit_wait_read();
        red_add(&sc->cnt[C_Z2], 1);
        TS(9);
      }
      __syncwarp();
    }
  }
  if (wg == 2) {
#pragma unroll 1
    for (int u = 72 + cta, k = 0; u < 216; u += NCTA, k ^= 1) {
      if (R < 0) { fence_async_smem(); bar_sync(4, 128); load_wm(u); }
      mbar_wait(full0 + 8 * B_WM, k);
      float acc[8] = {0.f, 0.f, 0.f, 0.f, 0.f, 0.f, 0.f, 0.f};
#pragma unroll 1
      for (int i = 0; i < 9; i++) mod_fma(acc, __uint_as_float(lds(red + 512 + ((t128 >> 1) + 64 * i) * 4)), lds4(sbase + O_NRM + t128 * 16 + i * 2048));
      mod_finish(p, acc, u, t128, red + 256 - 256 * k, tag16);
    }
    fence_async_smem();
    CK(13);
  }

  const int m1 = role & 15, grp = (role >> 4) & 15;
  const bool helper = (m1 & 3) == 3;
  const int f1 = 384 * grp + (helper ? 192 : 128) * (m1 >> 2);
  const int d1 = 160 * (m1 & 3), flip = m1 >= 7;
  const int a1bytes = helper ? 24576 : 16384;
  auto load_a1 = [&](int st, int kb) {
    mbar_expect(full0 + 8 * st, STAGE);
    tma4d_ef(sbase + st * STAGE, helper ? &maps.w1b : &maps.w1a, 4 * kb, f1 >> 6, full0 + 8 * st);
  };

  if (rows) {
#pragma unroll
    for (int kk = 0; kk < 4; kk++) af[kk] = __ldg(p.tab + TB_E + kk * 128 + t128);
    uint32_t tb[4], sy[6];
#pragma unroll
    for (int i = 0; i < 4; i++) tb[i] = pack_bf16(tmat(cta, 2 * t + 8 * (i & 1), 8 * (i >> 1) + g), tmat(cta, 2 * t + 8 * (i & 1) + 1, 8 * (i >> 1) + g));
#pragma unroll
    for (int i = 0; i < 6; i++) {
      const int rr = 16 * (wp & 3) + g + 8 * (i & 1);
      sy[i] = pin(sbase + O_Y + (t * 584 + 64 * ((3 * wg + (i >> 1) + 63 - rr) % 9) + rr) * 4);
    }
#pragma unroll
    for (int i = 0; i < 4; i++) tb[i] = pin(tb[i]);
    const int slot = 4 * (cta >> 4) + ((cta >> 1) & 3) + 32 * (2 * ((cta >> 3) & 1) + (cta & 1));
    const uint32_t* zin = sc->z2 + (size_t)slot * 4800;
    if (wg == 2) {
#pragma unroll 1
      for (int k = 0; k < 4; k++) {
        const int i = min(t128 + 128 * k, 431);
        uint4 v;
        int it = 0;
        while (true) {
          v = ld_rlx4(sc->mod + 2 * D_ + 4 * i);
          v.x ^= tag16; v.y ^= tag16; v.z ^= tag16; v.w ^= tag16;
          if (!any((v.x | v.y | v.z | v.w) & 0xffffu) || ++it > SPIN_MAX) break;
        }
        sts4(sbase + O_MOD + 16 * i, v.x, v.y, v.z, v.w);
      }
      CK(14);
      mbar_wait(full0 + 8 * B_Z2, 0);
      if (l == 0) {
        load_a1(wp - 8, wp - 8);
        if (wp > 8 && wp - 8 < NG1) prefetch_l2(reinterpret_cast<const uint8_t*>(p.w1) + (size_t)(128 * (cta >> 3) + 16 * (wp - 8) + 2 * (cta & 7)) * (2 * F_), 4 * F_);
      }
      __syncwarp();
    } else {
      uint32_t lo[9];
#pragma unroll
      for (int k1 = 0; k1 < 9; k1++) lo[k1] = pin(sbase + O_IN + line_off(k1, kap, 4 * wg + t, (cta >> 4) & 3));
      const uint32_t lx = pin(lo[0] + (kap ? 0 : 288 * 8));
      const uint32_t sb3 = pin(sbase + O_B3 + wg * 1024 + (l >> 4) * 2048 + (2 * (kap & 24) + (l & 15)) * 16);
      CK(14);
      if (wp == 0) {
        wait_cnt(&sc->cnt[C_Z2], 120 * ep);
        if (l == 0) {
          TS(14);
          mbar_expect(full0 + 8 * B_Z2, 19200);
          bulk_ld(sbase + O_IN, zin, 19200, full0 + 8 * B_Z2);
        }
        __syncwarp();
      }
      mbar_wait(full0 + 8 * B_Z2, 0);
      CK(15);
      if (tid == 0) TS(11);
      uint2 v[10];
      uint32_t bad = 0;
#pragma unroll
      for (int k1 = 0; k1 < 10; k1++) v[k1] = lds2(k1 < 9 ? lo[k1] : lx);
#pragma unroll
      for (int k1 = 0; k1 < 10; k1 += 2) bad |= diff2(v[k1].x, v[k1 + 1].x, tag1);
      if (__builtin_expect(any(bad & 1), 0)) {
        FAILCNT(1);
        int it = 0;
        do {
          bad = 0;
#pragma unroll
          for (int k1 = 0; k1 < 10; k1++) v[k1] = ld_rlx2(reinterpret_cast<const uint8_t*>(zin) + ((k1 < 9 ? lo[k1] : lx) - (sbase + O_IN)));
#pragma unroll
          for (int k1 = 0; k1 < 10; k1 += 2) bad |= diff2(v[k1].x, v[k1 + 1].x, tag1);
        } while (any(bad & 1) && ++it < SPIN_MAX);
      }
      float2 za[9], zb[9];
#pragma unroll
      for (int i = 0; i < 9; i++) { za[i] = make_float2(bf_lo(v[i].x), bf_hi(v[i].x)); zb[i] = make_float2(bf_lo(v[i].y), bf_hi(v[i].y)); }
      if (kap == 0) {
#pragma unroll
        for (int k = 1; k < 5; k++) {
          float2 a = za[k], b = za[9 - k];
          za[k] = make_float2(a.x - b.y, a.y + b.x); za[9 - k] = make_float2(a.x + b.y, b.x - a.y);
          a = zb[k]; b = zb[9 - k];
          zb[k] = make_float2(a.x - b.y, a.y + b.x); zb[9 - k] = make_float2(a.x + b.y, b.x - a.y);
        }
        za[0].y = bf_lo(v[9].x); zb[0].y = bf_lo(v[9].y);
      }
      __syncwarp();
      dft9(za); dft9(zb);
#pragma unroll
      for (int n = 0; n < 8; n += 2) {
        const int i0 = (9 - n) % 9, i1 = 8 - n;
        stmatrix4(sb3 + n * 2048, pack_bf16(za[i0].x, zb[i0].x), pack_bf16(za[i0].y, zb[i0].y), pack_bf16(za[i1].x, zb[i1].x), pack_bf16(za[i1].y, zb[i1].y));
      }
      stmatrix2(sb3 + 8 * 2048, pack_bf16(za[1].x, zb[1].x), pack_bf16(za[1].y, zb[1].y));
      fence_async_smem();
    }
    CK(16);
    __syncthreads();
    CK(17);
    float acc[24];
    const uint32_t db = (((sbase + O_B3 + wg * 6144) & 0x3FFFF) >> 4) | ((128 >> 4) << 16);
    wg_fence();
#pragma unroll
    for (int kk = 0; kk < 4; kk++) wgmma_rs_48(acc, af[kk].x, af[kk].y, af[kk].z, af[kk].w, db + kk * 16, 1024 >> 4, kk);
    wg_commit();
    uint32_t ga[9];
    uint2 sh[9], sw[9];
    if (wg < 2) {
#pragma unroll
      for (int i = 0; i < 9; i++) {
        const uint2 v = lds2(sbase + O_MOD + (64 * i + 2 * l) * 4);
        ga[i] = __byte_perm(v.x, v.y, 0x7632);
        sh[i] = lds2(sbase + O_MOD + (D_ + 64 * i + 2 * l) * 4);
        sw[i] = lds2(sbase + O_MOD + (2 * D_ + 64 * i + 2 * l) * 4);
      }
    }
    wg_wait<0>();
    reg_fence(acc);
    CK(18);
#pragma unroll
    for (int i = 0; i < 3; i++) {
      const float* a = &acc[8 * i];
      const uint32_t a0 = pack_bf16(a[0], a[1]), a1 = pack_bf16(a[2], a[3]), a2 = pack_bf16(a[4], a[5]), a3 = pack_bf16(a[6], a[7]);
#pragma unroll
      for (int jh = 0; jh < 2; jh++) {
        float y[4];
        mma16<false>(y, a0, a1, a2, a3, tb[2 * jh], tb[2 * jh + 1]);
        sts(sy[2 * i] + jh * (4 * 584 * 4), pack_bf16(y[0], y[1]));
        sts(sy[2 * i + 1] + jh * (4 * 584 * 4), pack_bf16(y[2], y[3]));
      }
    }
    CK(19);
    if (wg == 2) bar_arrive(7, NTHR);
    else {
      bar_sync(7, NTHR);
      CK(20);
      float a[18], b[18];
#pragma unroll
      for (int i = 0; i < 9; i++) {
        const uint2 y = lds2(sbase + O_Y + (wp * 584 + 64 * i + 2 * l) * 4);
        xr[i] = hfma2(ga[i], __byte_perm(y.x, y.y, 0x5410), xr[i]);
        xr[9 + i] = hfma2(ga[i], __byte_perm(y.x, y.y, 0x7632), xr[9 + i]);
        a[2 * i] = bf_lo(xr[i]); a[2 * i + 1] = bf_hi(xr[i]); b[2 * i] = bf_lo(xr[9 + i]); b[2 * i + 1] = bf_hi(xr[9 + i]);
      }
      float oa, ra, ob, rb;
      ln_stats2(a, b, 1.0f, oa, ra, ob, rb);
      CK(21);
#pragma unroll
      for (int i = 0; i < 9; i++) {
        const float c0 = __uint_as_float(sw[i].x), c1 = __uint_as_float(sw[i].y), s0 = __uint_as_float(sh[i].x), s1 = __uint_as_float(sh[i].y);
        a[2 * i] = fmaf(fmaf(a[2 * i], ra, oa), c0, s0); a[2 * i + 1] = fmaf(fmaf(a[2 * i + 1], ra, oa), c1, s1);
        b[2 * i] = fmaf(fmaf(b[2 * i], rb, ob), c0, s0); b[2 * i + 1] = fmaf(fmaf(b[2 * i + 1], rb, ob), c1, s1);
      }
      ln_stats2(a, b, 0.5f, oa, ra, ob, rb);
      CK(22);
      const uint32_t sh3 = sbase + O_IN + (l >> 4) * 1024 + wp * 128 + ((((l >> 2) ^ wp) & 3) << 4) + (l & 3) * 4;
#pragma unroll
      for (int i = 0; i < 9; i++) {
        sts(sh3 + i * 2048, pack_bf16(fmaf(a[2 * i], ra, oa), fmaf(a[2 * i + 1], ra, oa)));
        sts(sh3 + i * 2048 + 64, pack_bf16(fmaf(b[2 * i], rb, ob), fmaf(b[2 * i + 1], rb, ob)));
      }
      fence_async_smem();
      bar_arrive(8, 288);
      CK(23);
      const uint32_t sx = sbase + O_B3 + wp * 2304 + l * 4;
#pragma unroll
      for (int i = 0; i < 9; i++) { sts(sx + i * 128, xr[i]); sts(sx + 1152 + i * 128, xr[9 + i]); }
      fence_async_smem();
      bar_arrive(9, 288);
    }
  } else __syncthreads();
  asm volatile("barrier.cluster.wait.aligned;" ::: "memory");

  const bool g2 = q < 64;
  const int z2 = role >> 8;
  const int s2 = 128 * (z2 >> 2), d2 = 144 * (z2 & 3);
  const uint32_t rdy = full0 + 8 * B_RDY, rcv = full0 + 8 * B_RCV;
  constexpr int XST = (33 + 36 - JSK - 1) % NST;
  constexpr int ST0 = (32 - JSK - 1) % NST, ST1 = 31 % NST;

  if (wg == 2) {
    asm volatile("setmaxnreg.dec.sync.aligned.u32 40;");
    if (wp == 8) {
      int st = rows ? 4 : 0, ph = 1;
#pragma unroll 1
      for (int kb = st; kb < 32; kb++) {
        if (rows && kb < 6) mbar_wait(full0 + 8 * (B_S4 - 4 + kb), 0);
        mbar_wait(empty0 + 8 * st, ph);
        if (l == 0) {
          load_a1(st, kb);
          if (kb >= PF2K && kb < PF2K + PF2 && g2)
            prefetch_l2(reinterpret_cast<const uint8_t*>(p.w2) + (size_t)(36 * r + kb2_order(kb - PF2K)) * 262144 + q * 4096, 4096);
        }
        __syncwarp();
        ring_next<false>(st, ph);
      }
      if (g2) {
        st++;
#pragma unroll 1
        for (int i = 0; i < 36; i++) {
          if (i == HOLDA) mbar_wait(full0 + 8 * B_GO, 0);
          mbar_wait(empty0 + 8 * st, ph);
          if (l == 0) {
            mbar_expect(full0 + 8 * st, 16384 + 18432);
            tma3d_ef(sbase + st * STAGE, &maps.w2, 64 * (36 * r + kb2_order(i)), s2 >> 6, full0 + 8 * st);
          }
          __syncwarp();
          ring_next<true>(st, ph);
        }
      }
    } else if (wp >= 10) {
      const int sw = wp - 10;
      if (rows) {
        bar_sync(9 - sw, 288);
        if (!sw) mbar_wait(full0, 0);
        if (l == 0) {
          if (sw) {
            tma_st2d(&maps.h3, sbase + O_IN, 256 * (cta & 3), 18 * (cta >> 2));
            bulk_commit_wait();
            TS(1);
            mbar_arrive(full0 + 8 * B_S4);
            asm volatile("fence.acq_rel.gpu;" ::: "memory");
            red_add(&sc->cnt[C_H3 + (cta >> 2)], 1);
            TS(13);
          } else {
#pragma unroll 1
            for (int j = 0; j < 16; j++) bulk_st(sc->x1 + (size_t)(cta + 128 * j) * 288, sbase + O_B3 + j * 1152, 1152);
            bulk_commit_wait();
            mbar_arrive(full0 + 8 * B_S5);
          }
        }
        __syncwarp();
      }
      const uint32_t stg = sbase + (sw ? ST1 : ST0) * STAGE;
      const int kbA = (f1 >> 6) + (helper ? 2 : 1) * (sw ^ flip), kbB = helper ? (f1 >> 6) + 1 : kbA;
      const int dB = helper ? d1 + 32 * sw : d1 + 96;
      bar_sync(11 + sw, 160);
      if (l == 0) { TS(sw ? 31 : 30); bulk_st(sc->u + ((size_t)kbA * D_ + d1) * 128, stg, 96 * 128); }
      __syncwarp();
      bar_sync(13 + sw, 160);
      if (l == 0) {
        bulk_st(sc->u + ((size_t)kbB * D_ + dB) * 128, stg + 96 * 128, helper ? 32 * 128 : 64 * 128);
        if (helper) bulk_st(sc->u + ((size_t)kbB * D_ + d1 + 64 + 16 * sw) * 128, stg + 128 * 128, 16 * 128);
        bulk_commit_wait();
        mbar_arrive(empty0 + 8 * (sw ? ST1 : ST0));
        if (sw == 0) TS(26);
        asm volatile("fence.acq_rel.gpu;" ::: "memory");
        red_add(&sc->cnt[C_U + kbA], 2);
        if (helper) red_add(&sc->cnt[C_U + kbB], 1);
        TS(sw ? 23 : 17);
      }
      __syncwarp();
    } else {
      uint64_t ready = 0;
      int st = 0, ph = 1;
#pragma unroll 1
      for (int kb = 0; kb < 32; kb++) {
        if (rows && (kb >> 1) == 2) mbar_wait(full0 + 8 * (B_S4 - 4 + kb), 0);
        mbar_wait(empty0 + 8 * st, ph);
        wait_flags(sc->cnt + C_H3, 32, kb, 4 * ep, ready);
        if (l == 0) bulk_ld(sbase + st * STAGE + a1bytes, sc->h3 + ((size_t)(kb * 18 + (d1 >> 5)) << 12), STAGE - a1bytes, full0 + 8 * st);
        ring_next<false>(st, ph);
      }
      if (g2) {
        ready = 0;
        st++;
#pragma unroll 1
        for (int i = 0; i < 72; i++) {
          if (i == 36) ready = 0;
          const int kb = kb2_order(i < 36 ? i : i - 36), hf = r ^ (i >= 36);
          if (i <= 36) mbar_wait(empty0 + 8 * st, ph);
          wait_flags(sc->cnt + C_U + 36 * hf, 36, kb, 8 * ep, ready);
          if (i < 36) {
            if (l == 0) {
              bulk_ld(sbase + st * STAGE + 16384, sc->u + ((size_t)(36 * r + kb) * D_ + d2) * 128, 18432, full0 + 8 * st);
              if (i == GOAT) mbar_arrive(full0 + 8 * B_GO);
            }
            ring_next<true>(st, ph);
          } else if (ready == ~0ull) break;
        }
        if (l == 0) mbar_expect(full0 + 8 * XST, 18432);
        __syncwarp();
        if (l < 3) tma2d(sbase + XST * STAGE + 18432 + l * 6144, &maps.x1, d2 + 48 * l, s2 + 64 * (r ^ 1), full0 + 8 * XST);
        __syncwarp();
      }
    }
  } else {
    asm volatile("setmaxnreg.inc.sync.aligned.u32 232;");
    const int wgu = wg, ru = __shfl_sync(0xffffffffu, role, 0), flipu = (ru & 15) >= 7;
    const uint32_t sb4 = __shfl_sync(0xffffffffu, (sbase & 0x3FFFF) >> 4, 0), fullu = __shfl_sync(0xffffffffu, full0, 0);
    const int w = wp & 3;
    Ring rg = {0, 0};
    float acc[80];
    constexpr uint32_t LA = (8192 >> 4) << 16, LB = (4096 >> 4) << 16;
    {
      const int fa = f1 + (helper ? 128 : 64) * (wg ^ flip) + 16 * w + g, fb = helper ? f1 + 64 + 16 * w + g : fa;
      const float a0 = 0.5f * __bfloat162float(p.b1[fa]), a1 = 0.5f * __bfloat162float(p.b1[fa + 8]);
      const float b0 = 0.5f * __bfloat162float(p.b1[fb]), b1 = 0.5f * __bfloat162float(p.b1[fb + 8]);
#pragma unroll
      for (int i = 0; i < 80; i++) acc[i] = i < 48 ? ((i & 2) ? a1 : a0) : ((i & 2) ? b1 : b0);
      reg_fence(acc);
    }
    if ((ru & 3) != 3) gemm_main<0>(acc, sb4 + (wgu ^ flipu) * 512 + LA, 0, sb4 + 1024 + LB, 0, wgu, r, rg, fullu, rdy);
    else {
      float ac2[80];
#pragma unroll
      for (int i = 0; i < 72; i++) asm volatile("mov.b32 %0, %1;" : "=f"(ac2[i]) : "f"(acc[i]));
      gemm_main<1>(ac2, sb4 + (wgu ^ flipu) * 1024 + LA, sb4 + 512 + LA, sb4 + 1536 + LB, sb4 + 1536 + (wgu ? 256 + LB + (2 << 16) : 2 * LB), wgu, r, rg, fullu, rdy);
#pragma unroll
      for (int i = 0; i < 72; i++) asm volatile("mov.b32 %0, %1;" : "=f"(acc[i]) : "f"(ac2[i]));
    }
    if (t128 == 0) TS(wg ? 16 : 6);
    {
      const int mi = l >> 3, rr = l & 7;
      const uint32_t ad = sbase + (wg ? ST1 : ST0) * STAGE + (8 * (mi >> 1) + rr) * 128 + (((2 * w + (mi & 1)) ^ rr) << 4);
      float z[2][16];
#pragma unroll
      for (int j = -1; j <= 5; j++) {
        if (j >= 1) {
          const float* a = &acc[16 * (j - 1)];
          const float* tt = z[(j - 1) & 1];
#pragma unroll
          for (int h = 0; h < 16; h += 8)
            stmatrix4t(ad + (2 * (j - 1) + (h >> 3)) * 2048, pack_bf16(fmaf(a[h], tt[h], a[h]), fmaf(a[h + 1], tt[h + 1], a[h + 1])),
                       pack_bf16(fmaf(a[h + 2], tt[h + 2], a[h + 2]), fmaf(a[h + 3], tt[h + 3], a[h + 3])),
                       pack_bf16(fmaf(a[h + 4], tt[h + 4], a[h + 4]), fmaf(a[h + 5], tt[h + 5], a[h + 5])),
                       pack_bf16(fmaf(a[h + 6], tt[h + 6], a[h + 6]), fmaf(a[h + 7], tt[h + 7], a[h + 7])));
        }
        if (j >= 0 && j < 5) {
#pragma unroll
          for (int e = 0; e < 16; e++) asm("tanh.approx.f32 %0, %0;" : "+f"(z[j & 1][e]));
        }
        if (j < 4) {
#pragma unroll
          for (int e = 0; e < 16; e++) z[(j + 1) & 1][e] = gelu_arg(acc[16 * (j + 1) + e]);
        }
        if (j == 3 || j == 5) { fence_async_smem(); asm volatile("bar.arrive %0, 160;" ::"r"((j == 3 ? 11 : 13) + wgu) : "memory"); }
        if (j < 5) {
          if (j >= 0) reg_fence(z[j & 1]);
          if (j < 4) reg_fence(z[(j + 1) & 1]);
          if (__builtin_expect(sb4 == 0x7ffffff0u + j, 0)) __trap();
          reg_fence(acc);
        }
      }
      if (t128 == 0) TS(wg ? 29 : 28);
    }
    if (g2) {
      const int mb = wgu ^ r;
      uint32_t gb[18];
      {
        float a0 = 0.f, a1 = 0.f;
        if (wgu) {
          a0 = __bfloat162float(p.b2[s2 + 64 * mb + 16 * w + g]); a1 = __bfloat162float(p.b2[s2 + 64 * mb + 16 * w + 8 + g]);
          int it = 0;
          uint32_t bad;
          do {
            bad = 0;
#pragma unroll
            for (int i = 0; i < 18; i++) {
              const uint2 v = ld_rlx2(sc->mod + 5 * D_ + d2 + 8 * i + 2 * t);
              bad |= (v.x ^ tag16) | (v.y ^ tag16);
              gb[i] = __byte_perm(v.x, v.y, 0x7632);
            }
          } while (any(bad & 0xffffu) && ++it < SPIN_MAX);
        }
#pragma unroll
        for (int i = 0; i < 72; i++) acc[i] = (i & 2) ? a1 : a0;
      }
      rg.st++;
      gemm_main<3>(acc, sb4 + mb * 512 + LA, 0, sb4 + 1024 + (1 << 16), 0, wgu, r, rg, fullu, rdy);
      if (t128 == 0) TS(wg ? 20 : 19);
      const uint32_t sx = sbase + XST * STAGE;
      if (wgu == 0) {
        uint32_t rx, rb;
        asm("mapa.shared::cluster.u32 %0, %1, %2;" : "=r"(rx) : "r"(sx + t128 * 16), "r"(r ^ 1));
        asm("mapa.shared::cluster.u32 %0, %1, %2;" : "=r"(rb) : "r"(rcv), "r"(r ^ 1));
        mbar_wait_cluster(rdy, 0);
#pragma unroll
        for (int j = 0; j < 9; j++) {
          const float* a = &acc[8 * j];
          asm volatile("st.async.weak.shared::cluster.mbarrier::complete_tx::bytes.v4.b32 [%0], {%1,%2,%3,%4}, [%5];" ::"r"(rx + j * 2048),
                       "r"(pack_bf16(a[0], a[1])), "r"(pack_bf16(a[2], a[3])), "r"(pack_bf16(a[4], a[5])), "r"(pack_bf16(a[6], a[7])), "r"(rb) : "memory");
        }
        if (tid == 0) TS(21);
        if (w == 0) {
#pragma unroll 1
          for (int i = 0; i < 3; i++) {
            bar_sync(11 + i, 160);
            if (l == 0) tma_st2d(&maps.out, sx + 18432 + i * 6144, d2 + 48 * i, s2 + 64 * (r ^ 1));
            __syncwarp();
          }
          if (l == 0) { bulk_commit_wait_read(); TS(22); }
          __syncwarp();
        }
      } else {
        mbar_wait(fullu + 8 * XST, rg.ph);
        mbar_wait_cluster(rcv, 0);
        if (t128 == 0) TS(5);
        if (tid == 128 && cta == 0) sc->cnt[C_EP] = ep;
        const uint32_t xa = sx + 18432 + (16 * w + (l & 15)) * 96 + (l >> 4) * 16;
#pragma unroll
        for (int c = 0; c < 3; c++) {
          uint32_t pv[3][4], xv[3][4];
#pragma unroll
          for (int j = 0; j < 3; j++) {
            asm volatile("ld.shared.v4.b32 {%0,%1,%2,%3}, [%4];" : "=r"(pv[j][0]), "=r"(pv[j][1]), "=r"(pv[j][2]), "=r"(pv[j][3]) : "r"(sx + t128 * 16 + (3 * c + j) * 2048) : "memory");
            asm volatile("ldmatrix.sync.aligned.m8n8.x4.shared.b16 {%0,%1,%2,%3}, [%4];" : "=r"(xv[j][0]), "=r"(xv[j][1]), "=r"(xv[j][2]), "=r"(xv[j][3]) : "r"(xa + c * 6144 + j * 32) : "memory");
          }
#pragma unroll
          for (int j = 0; j < 3; j++) {
            const float* a = &acc[8 * (3 * c + j)];
            uint32_t o[4];
#pragma unroll
            for (int e = 0; e < 4; e++)
              o[e] = hadd2(xv[j][e], hmul2(gb[2 * (3 * c + j) + (e >> 1)], pack_bf16(a[2 * e] + bf_lo(pv[j][e]), a[2 * e + 1] + bf_hi(pv[j][e]))));
            stmatrix4(xa + c * 6144 + j * 32, o[0], o[1], o[2], o[3]);
          }
          fence_async_smem();
          asm volatile("bar.arrive %0, 160;" ::"r"(11 + c) : "memory");
        }
        if (t128 == 0) TS(7);
        __syncwarp();
      }
    }
  }
}

typedef CUresult (*EncodeFn)(CUtensorMap*, CUtensorMapDataType, cuuint32_t, void*, const cuuint64_t*, const cuuint64_t*, const cuuint32_t*,
                             const cuuint32_t*, CUtensorMapInterleave, CUtensorMapSwizzle, CUtensorMapL2promotion, CUtensorMapFloatOOBfill);

struct Dim { cuuint64_t n, stride; cuuint32_t box; };
template <int RANK>
void make_map(EncodeFn enc, CUtensorMap* m, bool words, bool swz, const void* ptr, const Dim (&d)[RANK]) {
  cuuint64_t gd[RANK], gs[RANK];
  cuuint32_t bx[RANK], es[RANK];
  for (int i = 0; i < RANK; i++) { gd[i] = d[i].n; gs[i] = d[i].stride; bx[i] = d[i].box; es[i] = 1; }
  enc(m, words ? CU_TENSOR_MAP_DATA_TYPE_UINT32 : CU_TENSOR_MAP_DATA_TYPE_BFLOAT16, RANK, const_cast<void*>(ptr), gd, gs + 1, bx, es,
      CU_TENSOR_MAP_INTERLEAVE_NONE, swz ? CU_TENSOR_MAP_SWIZZLE_128B : CU_TENSOR_MAP_SWIZZLE_NONE,
      swz ? CU_TENSOR_MAP_L2_PROMOTION_L2_256B : CU_TENSOR_MAP_L2_PROMOTION_NONE, CU_TENSOR_MAP_FLOAT_OOB_FILL_NONE);
}

}

extern "C" void kernel_launch(void* const* d_in, const int* in_sizes, int n_in, void* d_out, int out_size) {
  (void)in_sizes; (void)n_in; (void)out_size;
  static EncodeFn enc = nullptr;
  static void *sptr = nullptr, *tptr = nullptr;
  if (!enc) {
    void* f = nullptr; cudaDriverEntryPointQueryResult qr;
    cudaGetDriverEntryPoint("cuTensorMapEncodeTiled", &f, cudaEnableDefault, &qr);
    enc = reinterpret_cast<EncodeFn>(f);
    cudaFuncSetAttribute(fused_kernel, cudaFuncAttributeMaxDynamicSharedMemorySize, SMEM_BYTES);
    cudaGetSymbolAddress(&sptr, g_s);
    cudaGetSymbolAddress(&tptr, T_TAB);
  }
  Params p;
  p.x = (const __nv_bfloat16*)d_in[0]; p.wr = (const __nv_bfloat16*)d_in[1]; p.wi = (const __nv_bfloat16*)d_in[2];
  p.b1 = (const __nv_bfloat16*)d_in[5]; p.b2 = (const __nv_bfloat16*)d_in[7];
  p.c = (const __nv_bfloat16*)d_in[8]; p.wmod = (const __nv_bfloat16*)d_in[9];
  p.w1 = (const __nv_bfloat16*)d_in[4]; p.w2 = (const __nv_bfloat16*)d_in[6];
  p.s = static_cast<Scratch*>(sptr); p.tab = static_cast<const uint4*>(tptr);
  Maps maps;
  make_map<4>(enc, &maps.w1a, false, true, p.w1, {{64, 0, 64}, {16, 128 * 2 * F_, 16}, {128, 2 * F_, 4}, {72, 128, 2}});
  make_map<4>(enc, &maps.w1b, false, true, p.w1, {{64, 0, 64}, {16, 128 * 2 * F_, 16}, {128, 2 * F_, 4}, {72, 128, 3}});
  make_map<3>(enc, &maps.w2, false, true, p.w2, {{64, 0, 64}, {F_, 2 * S_, 64}, {32, 128, 2}});
  make_map<2>(enc, &maps.x1, false, false, p.s->x1, {{D_, 0, 48}, {S_, 2 * D_, 64}});
  make_map<2>(enc, &maps.out, false, false, d_out, {{D_, 0, 48}, {S_, 2 * D_, 64}});
  make_map<2>(enc, &maps.z1, true, false, p.s->z1, {{5120, 0, 40}, {120, 20480, 60}});
  make_map<2>(enc, &maps.z2, true, false, p.s->z2, {{4800, 0, 40}, {128, 19200, 128}});
  make_map<2>(enc, &maps.wr, false, false, p.wr, {{16 * DF_, 0, 40}, {128, 32 * DF_, 128}});
  make_map<2>(enc, &maps.wi, false, false, p.wi, {{16 * DF_, 0, 40}, {128, 32 * DF_, 128}});
  make_map<2>(enc, &maps.wm, false, false, p.wmod, {{6 * D_, 0, 16}, {D_, 12 * D_, 192}});
  make_map<2>(enc, &maps.h3, true, false, p.s->h3, {{1024, 0, 256}, {32 * 18, 4096, 18}});
  cudaLaunchConfig_t cfg = {};
  cfg.gridDim = dim3(NCTA); cfg.blockDim = dim3(NTHR); cfg.dynamicSmemBytes = SMEM_BYTES; cfg.stream = cudaStreamPerThread;
  cudaLaunchAttribute at[1];
  at[0].id = cudaLaunchAttributeClusterDimension; at[0].val.clusterDim.x = 2; at[0].val.clusterDim.y = 1; at[0].val.clusterDim.z = 1;
  cfg.attrs = at; cfg.numAttrs = 1;
  cudaLaunchKernelEx(&cfg, fused_kernel, p, maps);
}
```

```cpp
#include <cuda_runtime.h>
#include <cuda_bf16.h>
#include <cuda.h>
#include <stdint.h>

namespace {

constexpr int S_ = 2048, D_ = 576, DF_ = 289, F_ = 4608;
constexpr int NCTA = 132, NTHR = 384;
constexpr int STAGE = 36864, NST = 6;
constexpr int SMEM_BYTES = NST * STAGE + 1024;
constexpr int O_NRM = 0, O_B1 = 19456, O_Z1 = 38912, O_P2 = 59392;
constexpr int O_RAW = 4 * STAGE;
constexpr int O_IN = 4 * STAGE, O_Y = O_IN + 19456, O_B3 = O_IN + 38912, O_MOD = O_IN + 57344;

__device__ __align__(128) const uint32_t T_TAB[5632] = {
0x3f803f80,0xbf803f80,0x3f803f80,0xbf803f80,0x3f803f80,0xbf803f80,0x3f803f80,0xbf803f80,0x3f803f80,0xbf803f80,0x3f803f80,0xbf803f80,
0x3f803f80,0xbf803f80,0x3f803f80,0xbf803f80,0x3f7f3f80,0xbdc90000,0x3f223f35,0xbf46bf35,0x3f753f7b,0xbe95be48,0x3ef13f0e,0xbf62bf55,
0x3f623f6d,0xbef1bec4,0x3e953ec4,0xbf75bf6d,0x3f463f55,0xbf22bf0e,0x3dc93e48,0xbf7fbf7b,0x3f7b3f80,0xbe480000,0xbe480000,0xbf7bbf80,
0x3f553f6d,0xbf0ebec4,0xbf0ebec4,0xbf55bf6d,0x3f0e3f35,0xbf55bf35,0xbf55bf35,0xbf0ebf35,0x3e483ec4,0xbf7bbf6d,0xbf7bbf6d,0xbe48bec4,
0x3f753f80,0xbe950000,0xbf62bf35,0xbef1bf35,0x3f223f55,0xbf46bf0e,0xbf7fbf7b,0x3dc9be48,0x3dc93ec4,0xbf7fbf6d,0xbf46bf6d,0x3f223ec4,
0xbef1be48,0xbf62bf7b,0xbe95bf0e,0x3f753f55,0x3f6d3f80,0xbec40000,0xbf6dbf80,0x3ec40000,0x3ec43f35,0xbf6dbf35,0xbec4bf35,0x3f6d3f35,
0xbec40000,0xbf6dbf80,0x3ec40000,0x3f6d3f80,0xbf6dbf35,0xbec4bf35,0x3f6d3f35,0x3ec43f35,0x3f623f80,0xbef10000,0xbe95bf35,0x3f753f35,
0x3dc93f0e,0xbf7fbf55,0x3f223e48,0x3f463f7b,0xbf46bec4,0xbf22bf6d,0x3f7f3f6d,0xbdc93ec4,0xbf75bf7b,0x3e95be48,0x3ef13f55,0xbf62bf0e,
0x3f553f80,0xbf0e0000,0x3f0e0000,0x3f553f80,0xbe483ec4,0xbf7bbf6d,0x3f7b3f6d,0xbe483ec4,0xbf7bbf35,0xbe48bf35,0x3e483f35,0xbf7bbf35,
0xbf0ebf6d,0x3f553ec4,0xbf55bec4,0xbf0ebf6d,0x3f463f80,0xbf220000,0x3f7f3f35,0x3dc93f35,0xbef13e48,0xbf62bf7b,0x3e953f55,0xbf75bf0e,
0xbf75bf6d,0x3e95bec4,0xbf62bec4,0xbef1bf6d,0x3dc9bf0e,0x3f7f3f55,0xbf22bf7b,0x3f463e48,0x3f353f80,0xbf350000,0x3f353f80,0xbf350000,
0xbf350000,0xbf35bf80,0xbf350000,0xbf35bf80,0xbf35bf80,0x3f350000,0xbf35bf80,0x3f350000,0x3f350000,0x3f353f80,0x3f350000,0x3f353f80,
0x3f223f80,0xbf460000,0xbdc93f35,0xbf7fbf35,0xbf62be48,0xbef1bf7b,0xbf75bf55,0x3e95bf0e,0xbe95bf6d,0x3f753ec4,0x3ef1bec4,0x3f623f6d,
0x3f7f3f0e,0x3dc93f55,0x3f463f7b,0xbf223e48,0x3f0e3f80,0xbf550000,0xbf550000,0xbf0ebf80,0xbf7bbec4,0xbe48bf6d,0xbe48bf6d,0x3f7b3ec4,
0x3e48bf35,0x3f7b3f35,0x3f7b3f35,0xbe483f35,0x3f553f6d,0xbf0e3ec4,0xbf0e3ec4,0xbf55bf6d,0x3ef13f80,0xbf620000,0xbf75bf35,0x3e95bf35,
0xbf7fbf0e,0x3dc9bf55,0x3f46be48,0x3f223f7b,0x3f22bec4,0x3f463f6d,0x3dc93f6d,0xbf7fbec4,0x3e953f7b,0xbf75be48,0xbf62bf55,0x3ef1bf0e,
0x3ec43f80,0xbf6d0000,0xbec4bf80,0x3f6d0000,0xbf6dbf35,0x3ec4bf35,0x3f6d3f35,0xbec43f35,0x3f6d0000,0x3ec43f80,0xbf6d0000,0xbec4bf80,
0xbec43f35,0xbf6dbf35,0x3ec4bf35,0x3f6d3f35,0x3e953f80,0xbf750000,0x3ef1bf35,0x3f623f35,0xbf46bf55,0x3f22bf0e,0x3dc93f7b,0xbf7fbe48,
0x3f7f3ec4,0xbdc93f6d,0xbf22bf6d,0x3f46bec4,0xbf623e48,0xbef1bf7b,0x3f753f0e,0xbe953f55,0x3e483f80,0xbf7b0000,0x3f7b0000,0x3e483f80,
0xbf0ebf6d,0x3f55bec4,0xbf553ec4,0xbf0ebf6d,0x3f553f35,0xbf0e3f35,0x3f0ebf35,0x3f553f35,0xbf7bbec4,0x3e48bf6d,0xbe483f6d,0xbf7bbec4,
0x3dc93f80,0xbf7f0000,0x3f463f35,0xbf223f35,0xbe95bf7b,0x3f75be48,0xbf62bf0e,0x3ef1bf55,0x3ef13f6d,0xbf623ec4,0x3f753ec4,0xbe953f6d,
0xbf22bf55,0x3f46bf0e,0xbf7fbe48,0x3dc9bf7b,0x3f80,0xbf800000,0x3f80,0xbf800000,0xbf80,0x3f800000,0xbf80,0x3f800000,
0x3f80,0xbf800000,0x3f80,0xbf800000,0xbf80,0x3f800000,0xbf80,0x3f800000,0xbdc93f80,0xbf7f0000,0xbf463f35,0xbf22bf35,
0x3e95bf7b,0x3f753e48,0x3f62bf0e,0x3ef13f55,0xbef13f6d,0xbf62bec4,0xbf753ec4,0xbe95bf6d,0x3f22bf55,0x3f463f0e,0x3f7fbe48,0x3dc93f7b,
0xbe483f80,0xbf7b0000,0xbf7b0000,0x3e48bf80,0x3f0ebf6d,0x3f553ec4,0x3f553ec4,0xbf0e3f6d,0xbf553f35,0xbf0ebf35,0xbf0ebf35,0x3f55bf35,
0x3f7bbec4,0x3e483f6d,0x3e483f6d,0xbf7b3ec4,0xbe953f80,0xbf750000,0xbef1bf35,0x3f62bf35,0x3f46bf55,0x3f223f0e,0xbdc93f7b,0xbf7f3e48,
0xbf7f3ec4,0xbdc9bf6d,0x3f22bf6d,0x3f463ec4,0x3f623e48,0xbef13f7b,0xbf753f0e,0xbe95bf55,0xbec43f80,0xbf6d0000,0x3ec4bf80,0x3f6d0000,
0x3f6dbf35,0x3ec43f35,0xbf6d3f35,0xbec4bf35,0xbf6d0000,0x3ec4bf80,0x3f6d0000,0xbec43f80,0x3ec43f35,0xbf6d3f35,0xbec4bf35,0x3f6dbf35,
0xbef13f80,0xbf620000,0x3f75bf35,0x3e953f35,0x3f7fbf0e,0x3dc93f55,0xbf46be48,0x3f22bf7b,0xbf22bec4,0x3f46bf6d,0xbdc93f6d,0xbf7f3ec4,
0xbe953f7b,0xbf753e48,0x3f62bf55,0x3ef13f0e,0xbf0e3f80,0xbf550000,0x3f550000,0xbf0e3f80,0x3f7bbec4,0xbe483f6d,0x3e48bf6d,0x3f7bbec4,
0xbe48bf35,0x3f7bbf35,0xbf7b3f35,0xbe48bf35,0xbf553f6d,0xbf0ebec4,0x3f0e3ec4,0xbf553f6d,0xbf223f80,0xbf460000,0x3dc93f35,0xbf7f3f35,
0x3f62be48,0xbef13f7b,0x3f75bf55,0x3e953f0e,0x3e95bf6d,0x3f75bec4,0xbef1bec4,0x3f62bf6d,0xbf7f3f0e,0x3dc9bf55,0xbf463f7b,0xbf22be48,
0xbf353f80,0xbf350000,0xbf353f80,0xbf350000,0x3f350000,0xbf353f80,0x3f350000,0xbf353f80,0x3f35bf80,0x3f350000,0x3f35bf80,0x3f350000,
0xbf350000,0x3f35bf80,0xbf350000,0x3f35bf80,0xbf463f80,0xbf220000,0xbf7f3f35,0x3dc9bf35,0x3ef13e48,0xbf623f7b,0xbe953f55,0xbf753f0e,
0x3f75bf6d,0x3e953ec4,0x3f62bec4,0xbef13f6d,0xbdc9bf0e,0x3f7fbf55,0x3f22bf7b,0x3f46be48,0xbf553f80,0xbf0e0000,0xbf0e0000,0x3f55bf80,
0x3e483ec4,0xbf7b3f6d,0xbf7b3f6d,0xbe48bec4,0x3f7bbf35,0xbe483f35,0xbe483f35,0xbf7b3f35,0x3f0ebf6d,0x3f55bec4,0x3f55bec4,0xbf0e3f6d,
0xbf623f80,0xbef10000,0x3e95bf35,0x3f75bf35,0xbdc93f0e,0xbf7f3f55,0xbf223e48,0x3f46bf7b,0x3f46bec4,0xbf223f6d,0xbf7f3f6d,0xbdc9bec4,
0x3f75bf7b,0x3e953e48,0xbef13f55,0xbf623f0e,0xbf6d3f80,0xbec40000,0x3f6dbf80,0x3ec40000,0xbec43f35,0xbf6d3f35,0x3ec4bf35,0x3f6dbf35,
0x3ec40000,0xbf6d3f80,0xbec40000,0x3f6dbf80,0x3f6dbf35,0xbec43f35,0xbf6d3f35,0x3ec4bf35,0xbf753f80,0xbe950000,0x3f62bf35,0xbef13f35,
0xbf223f55,0xbf463f0e,0x3f7fbf7b,0x3dc93e48,0xbdc93ec4,0xbf7f3f6d,0x3f46bf6d,0x3f22bec4,0x3ef1be48,0xbf623f7b,0x3e95bf0e,0x3f75bf55,
0xbf7b3f80,0xbe480000,0x3e480000,0xbf7b3f80,0xbf553f6d,0xbf0e3ec4,0x3f0ebec4,0xbf553f6d,0xbf0e3f35,0xbf553f35,0x3f55bf35,0xbf0e3f35,
0xbe483ec4,0xbf7b3f6d,0x3f7bbf6d,0xbe483ec4,0xbf7f3f80,0xbdc90000,0xbf223f35,0xbf463f35,0xbf753f7b,0xbe953e48,0xbef13f0e,0xbf623f55,
0xbf623f6d,0xbef13ec4,0xbe953ec4,0xbf753f6d,0xbf463f55,0xbf223f0e,0xbdc93e48,0xbf7f3f7b,0x3f803f80,0xbf803f80,0x3f803f80,0xbf803f80,
0x3f803f80,0xbf803f80,0x3f803f80,0xbf803f80,0x3f803f80,0xbf803f80,0x3f803f80,0xbf803f80,0x3f803f80,0xbf803f80,0x3f803f80,0xbf803f80,
0xbdc90000,0xbf7fbf80,0xbf46bf35,0xbf22bf35,0xbe95be48,0xbf75bf7b,0xbf62bf55,0xbef1bf0e,0xbef1bec4,0xbf62bf6d,0xbf75bf6d,0xbe95bec4,
0xbf22bf0e,0xbf46bf55,0xbf7fbf7b,0xbdc9be48,0xbf7bbf80,0x3e480000,0x3e480000,0x3f7b3f80,0xbf55bf6d,0x3f0e3ec4,0x3f0e3ec4,0x3f553f6d,
0xbf0ebf35,0x3f553f35,0x3f553f35,0x3f0e3f35,0xbe48bec4,0x3f7b3f6d,0x3f7b3f6d,0x3e483ec4,0x3e950000,0x3f753f80,0x3ef13f35,0xbf62bf35,
0x3f463f0e,0x3f223f55,0xbdc93e48,0xbf7fbf7b,0x3f7f3f6d,0x3dc93ec4,0xbf22bec4,0xbf46bf6d,0x3f623f7b,0xbef1be48,0xbf75bf55,0xbe95bf0e,
0x3f6d3f80,0xbec40000,0xbf6dbf80,0x3ec40000,0x3ec43f35,0xbf6dbf35,0xbec4bf35,0x3f6d3f35,0xbec40000,0xbf6dbf80,0x3ec40000,0x3f6d3f80,
0xbf6dbf35,0xbec4bf35,0x3f6d3f35,0x3ec43f35,0xbef10000,0xbf62bf80,0x3f753f35,0x3e953f35,0xbf7fbf55,0xbdc9bf0e,0x3f463f7b,0xbf22be48,
0xbf22bf6d,0x3f463ec4,0xbdc93ec4,0xbf7fbf6d,0x3e95be48,0x3f753f7b,0xbf62bf0e,0xbef1bf55,0xbf55bf80,0x3f0e0000,0xbf0e0000,0xbf55bf80,
0x3e48bec4,0x3f7b3f6d,0xbf7bbf6d,0x3e48bec4,0x3f7b3f35,0x3e483f35,0xbe48bf35,0x3f7b3f35,0x3f0e3f6d,0xbf55bec4,0x3f553ec4,0x3f0e3f6d,
0x3f220000,0x3f463f80,0xbdc9bf35,0x3f7f3f35,0x3f623f7b,0xbef13e48,0x3f753f0e,0x3e953f55,0xbe953ec4,0xbf75bf6d,0x3ef13f6d,0xbf62bec4,
0xbf7fbf55,0x3dc9bf0e,0xbf46be48,0xbf22bf7b,0x3f353f80,0xbf350000,0x3f353f80,0xbf350000,0xbf350000,0xbf35bf80,0xbf350000,0xbf35bf80,
0xbf35bf80,0x3f350000,0xbf35bf80,0x3f350000,0x3f350000,0x3f353f80,0x3f350000,0x3f353f80,0xbf460000,0xbf22bf80,0xbf7fbf35,0x3dc9bf35,
0xbef1bf7b,0x3f623e48,0x3e95bf0e,0x3f753f55,0x3f753ec4,0x3e953f6d,0x3f623f6d,0xbef13ec4,0x3dc93f55,0xbf7fbf0e,0xbf223e48,0xbf46bf7b,
0xbf0ebf80,0x3f550000,0x3f550000,0x3f0e3f80,0x3f7b3ec4,0x3e483f6d,0x3e483f6d,0xbf7bbec4,0xbe483f35,0xbf7bbf35,0xbf7bbf35,0x3e48bf35,
0xbf55bf6d,0x3f0ebec4,0x3f0ebec4,0x3f553f6d,0x3f620000,0x3ef13f80,0xbe953f35,0xbf75bf35,0xbdc93f55,0xbf7fbf0e,0xbf22bf7b,0x3f46be48,
0xbf46bf6d,0x3f22bec4,0x3f7f3ec4,0x3dc93f6d,0x3f753e48,0x3e953f7b,0xbef13f0e,0xbf62bf55,0x3ec43f80,0xbf6d0000,0xbec4bf80,0x3f6d0000,
0xbf6dbf35,0x3ec4bf35,0x3f6d3f35,0xbec43f35,0x3f6d0000,0x3ec43f80,0xbf6d0000,0xbec4bf80,0xbec43f35,0xbf6dbf35,0x3ec4bf35,0x3f6d3f35,
0xbf750000,0xbe95bf80,0x3f623f35,0xbef13f35,0x3f22bf0e,0x3f463f55,0xbf7fbe48,0xbdc9bf7b,0xbdc93f6d,0xbf7fbec4,0x3f46bec4,0x3f223f6d,
0xbef1bf7b,0x3f62be48,0xbe953f55,0xbf75bf0e,0xbe48bf80,0x3f7b0000,0xbf7b0000,0xbe48bf80,0x3f0e3f6d,0xbf553ec4,0x3f55bec4,0x3f0e3f6d,
0xbf55bf35,0x3f0ebf35,0xbf0e3f35,0xbf55bf35,0x3f7b3ec4,0xbe483f6d,0x3e48bf6d,0x3f7b3ec4,0x3f7f0000,0x3dc93f80,0x3f22bf35,0x3f463f35,
0xbf753e48,0xbe95bf7b,0xbef13f55,0xbf62bf0e,0x3f62bec4,0x3ef13f6d,0x3e95bf6d,0x3f753ec4,0xbf463f0e,0xbf22bf55,0xbdc93f7b,0xbf7fbe48,
0x3f80,0xbf800000,0x3f80,0xbf800000,0xbf80,0x3f800000,0xbf80,0x3f800000,0x3f80,0xbf800000,0x3f80,0xbf800000,
0xbf80,0x3f800000,0xbf80,0x3f800000,0xbf7f0000,0x3dc9bf80,0xbf22bf35,0x3f46bf35,0x3f753e48,0xbe953f7b,0x3ef13f55,0xbf623f0e,
0xbf62bec4,0x3ef1bf6d,0xbe95bf6d,0x3f75bec4,0x3f463f0e,0xbf223f55,0x3dc93f7b,0xbf7f3e48,0x3e48bf80,0x3f7b0000,0x3f7b0000,0xbe483f80,
0xbf0e3f6d,0xbf55bec4,0xbf55bec4,0x3f0ebf6d,0x3f55bf35,0x3f0e3f35,0x3f0e3f35,0xbf553f35,0xbf7b3ec4,0xbe48bf6d,0xbe48bf6d,0x3f7bbec4,
0x3f750000,0xbe953f80,0xbf623f35,0xbef1bf35,0xbf22bf0e,0x3f46bf55,0x3f7fbe48,0xbdc93f7b,0x3dc93f6d,0xbf7f3ec4,0xbf46bec4,0x3f22bf6d,
0x3ef1bf7b,0x3f623e48,0x3e953f55,0xbf753f0e,0xbec43f80,0xbf6d0000,0x3ec4bf80,0x3f6d0000,0x3f6dbf35,0x3ec43f35,0xbf6d3f35,0xbec4bf35,
0xbf6d0000,0x3ec4bf80,0x3f6d0000,0xbec43f80,0x3ec43f35,0xbf6d3f35,0xbec4bf35,0x3f6dbf35,0xbf620000,0x3ef1bf80,0x3e953f35,0xbf753f35,
0x3dc93f55,0xbf7f3f0e,0x3f22bf7b,0x3f463e48,0x3f46bf6d,0x3f223ec4,0xbf7f3ec4,0x3dc9bf6d,0xbf753e48,0x3e95bf7b,0x3ef13f0e,0xbf623f55,
0x3f0ebf80,0x3f550000,0xbf550000,0x3f0ebf80,0xbf7b3ec4,0x3e48bf6d,0xbe483f6d,0xbf7b3ec4,0x3e483f35,0xbf7b3f35,0x3f7bbf35,0x3e483f35,
0x3f55bf6d,0x3f0e3ec4,0xbf0ebec4,0x3f55bf6d,0x3f460000,0xbf223f80,0x3f7fbf35,0x3dc93f35,0x3ef1bf7b,0x3f62be48,0xbe95bf0e,0x3f75bf55,
0xbf753ec4,0x3e95bf6d,0xbf623f6d,0xbef1bec4,0xbdc93f55,0xbf7f3f0e,0x3f223e48,0xbf463f7b,0xbf353f80,0xbf350000,0xbf353f80,0xbf350000,
0x3f350000,0xbf353f80,0x3f350000,0xbf353f80,0x3f35bf80,0x3f350000,0x3f35bf80,0x3f350000,0xbf350000,0x3f35bf80,0xbf350000,0x3f35bf80,
0xbf220000,0x3f46bf80,0x3dc9bf35,0x3f7fbf35,0xbf623f7b,0xbef1be48,0xbf753f0e,0x3e95bf55,0x3e953ec4,0xbf753f6d,0xbef13f6d,0xbf623ec4,
0x3f7fbf55,0x3dc93f0e,0x3f46be48,0xbf223f7b,0x3f55bf80,0x3f0e0000,0x3f0e0000,0xbf553f80,0xbe48bec4,0x3f7bbf6d,0x3f7bbf6d,0x3e483ec4,
0xbf7b3f35,0x3e48bf35,0x3e48bf35,0x3f7bbf35,0xbf0e3f6d,0xbf553ec4,0xbf553ec4,0x3f0ebf6d,0x3ef10000,0xbf623f80,0xbf753f35,0x3e95bf35,
0x3f7fbf55,0xbdc93f0e,0xbf463f7b,0xbf223e48,0x3f22bf6d,0x3f46bec4,0x3dc93ec4,0xbf7f3f6d,0xbe95be48,0x3f75bf7b,0x3f62bf0e,0xbef13f55,
0xbf6d3f80,0xbec40000,0x3f6dbf80,0x3ec40000,0xbec43f35,0xbf6d3f35,0x3ec4bf35,0x3f6dbf35,0x3ec40000,0xbf6d3f80,0xbec40000,0x3f6dbf80,
0x3f6dbf35,0xbec43f35,0xbf6d3f35,0x3ec4bf35,0xbe950000,0x3f75bf80,0xbef13f35,0xbf623f35,0xbf463f0e,0x3f22bf55,0x3dc93e48,0xbf7f3f7b,
0xbf7f3f6d,0x3dc9bec4,0x3f22bec4,0xbf463f6d,0xbf623f7b,0xbef13e48,0x3f75bf55,0xbe953f0e,0x3f7bbf80,0x3e480000,0xbe480000,0x3f7bbf80,
0x3f55bf6d,0x3f0ebec4,0xbf0e3ec4,0x3f55bf6d,0x3f0ebf35,0x3f55bf35,0xbf553f35,0x3f0ebf35,0x3e48bec4,0x3f7bbf6d,0xbf7b3f6d,0x3e48bec4,
0x3dc90000,0xbf7f3f80,0x3f46bf35,0xbf223f35,0x3e95be48,0xbf753f7b,0x3f62bf55,0xbef13f0e,0x3ef1bec4,0xbf623f6d,0x3f75bf6d,0xbe953ec4,
0x3f22bf0e,0xbf463f55,0x3f7fbf7b,0xbdc93e48,0x3f803f80,0xbf803f80,0x3f803f80,0xbf803f80,0x3f803f80,0xbf803f80,0x3f803f80,0xbf803f80,
0x3f803f80,0xbf803f80,0x3f803f80,0xbf803f80,0x3f803f80,0xbf803f80,0x3f803f80,0xbf803f80,0xbf7fbf80,0x3dc90000,0xbf22bf35,0x3f463f35,
0xbf75bf7b,0x3e953e48,0xbef1bf0e,0x3f623f55,0xbf62bf6d,0x3ef13ec4,0xbe95bec4,0x3f753f6d,0xbf46bf55,0x3f223f0e,0xbdc9be48,0x3f7f3f7b,
0x3f7b3f80,0xbe480000,0xbe480000,0xbf7bbf80,0x3f553f6d,0xbf0ebec4,0xbf0ebec4,0xbf55bf6d,0x3f0e3f35,0xbf55bf35,0xbf55bf35,0xbf0ebf35,
0x3e483ec4,0xbf7bbf6d,0xbf7bbf6d,0xbe48bec4,0xbf75bf80,0x3e950000,0x3f623f35,0x3ef13f35,0xbf22bf55,0x3f463f0e,0x3f7f3f7b,0xbdc93e48,
0xbdc9bec4,0x3f7f3f6d,0x3f463f6d,0xbf22bec4,0x3ef13e48,0x3f623f7b,0x3e953f0e,0xbf75bf55,0x3f6d3f80,0xbec40000,0xbf6dbf80,0x3ec40000,
0x3ec43f35,0xbf6dbf35,0xbec4bf35,0x3f6d3f35,0xbec40000,0xbf6dbf80,0x3ec40000,0x3f6d3f80,0xbf6dbf35,0xbec4bf35,0x3f6d3f35,0x3ec43f35,
0xbf62bf80,0x3ef10000,0x3e953f35,0xbf75bf35,0xbdc9bf0e,0x3f7f3f55,0xbf22be48,0xbf46bf7b,0x3f463ec4,0x3f223f6d,0xbf7fbf6d,0x3dc9bec4,
0x3f753f7b,0xbe953e48,0xbef1bf55,0x3f623f0e,0x3f553f80,0xbf0e0000,0x3f0e0000,0x3f553f80,0xbe483ec4,0xbf7bbf6d,0x3f7b3f6d,0xbe483ec4,
0xbf7bbf35,0xbe48bf35,0x3e483f35,0xbf7bbf35,0xbf0ebf6d,0x3f553ec4,0xbf55bec4,0xbf0ebf6d,0xbf46bf80,0x3f220000,0xbf7fbf35,0xbdc9bf35,
0x3ef1be48,0x3f623f7b,0xbe95bf55,0x3f753f0e,0x3f753f6d,0xbe953ec4,0x3f623ec4,0x3ef13f6d,0xbdc93f0e,0xbf7fbf55,0x3f223f7b,0xbf46be48,
0x3f353f80,0xbf350000,0x3f353f80,0xbf350000,0xbf350000,0xbf35bf80,0xbf350000,0xbf35bf80,0xbf35bf80,0x3f350000,0xbf35bf80,0x3f350000,
0x3f350000,0x3f353f80,0x3f350000,0x3f353f80,0xbf22bf80,0x3f460000,0x3dc9bf35,0x3f7f3f35,0x3f623e48,0x3ef13f7b,0x3f753f55,0xbe953f0e,
0x3e953f6d,0xbf75bec4,0xbef13ec4,0xbf62bf6d,0xbf7fbf0e,0xbdc9bf55,0xbf46bf7b,0x3f22be48,0x3f0e3f80,0xbf550000,0xbf550000,0xbf0ebf80,
0xbf7bbec4,0xbe48bf6d,0xbe48bf6d,0x3f7b3ec4,0x3e48bf35,0x3f7b3f35,0x3f7b3f35,0xbe483f35,0x3f553f6d,0xbf0e3ec4,0xbf0e3ec4,0xbf55bf6d,
0xbef1bf80,0x3f620000,0x3f753f35,0xbe953f35,0x3f7f3f0e,0xbdc93f55,0xbf463e48,0xbf22bf7b,0xbf223ec4,0xbf46bf6d,0xbdc9bf6d,0x3f7f3ec4,
0xbe95bf7b,0x3f753e48,0x3f623f55,0xbef13f0e,0x3ec43f80,0xbf6d0000,0xbec4bf80,0x3f6d0000,0xbf6dbf35,0x3ec4bf35,0x3f6d3f35,0xbec43f35,
0x3f6d0000,0x3ec43f80,0xbf6d0000,0xbec4bf80,0xbec43f35,0xbf6dbf35,0x3ec4bf35,0x3f6d3f35,0xbe95bf80,0x3f750000,0xbef13f35,0xbf62bf35,
0x3f463f55,0xbf223f0e,0xbdc9bf7b,0x3f7f3e48,0xbf7fbec4,0x3dc9bf6d,0x3f223f6d,0xbf463ec4,0x3f62be48,0x3ef13f7b,0xbf75bf0e,0x3e95bf55,
0x3e483f80,0xbf7b0000,0x3f7b0000,0x3e483f80,0xbf0ebf6d,0x3f55bec4,0xbf553ec4,0xbf0ebf6d,0x3f553f35,0xbf0e3f35,0x3f0ebf35,0x3f553f35,
0xbf7bbec4,0x3e48bf6d,0xbe483f6d,0xbf7bbec4,0xbdc9bf80,0x3f7f0000,0xbf46bf35,0x3f22bf35,0x3e953f7b,0xbf753e48,0x3f623f0e,0xbef13f55,
0xbef1bf6d,0x3f62bec4,0xbf75bec4,0x3e95bf6d,0x3f223f55,0xbf463f0e,0x3f7f3e48,0xbdc93f7b,0x3f80,0xbf800000,0x3f80,0xbf800000,
0xbf80,0x3f800000,0xbf80,0x3f800000,0x3f80,0xbf800000,0x3f80,0xbf800000,0xbf80,0x3f800000,0xbf80,0x3f800000,
0x3dc9bf80,0x3f7f0000,0x3f46bf35,0x3f223f35,0xbe953f7b,0xbf75be48,0xbf623f0e,0xbef1bf55,0x3ef1bf6d,0x3f623ec4,0x3f75bec4,0x3e953f6d,
0xbf223f55,0xbf46bf0e,0xbf7f3e48,0xbdc9bf7b,0xbe483f80,0xbf7b0000,0xbf7b0000,0x3e48bf80,0x3f0ebf6d,0x3f553ec4,0x3f553ec4,0xbf0e3f6d,
0xbf553f35,0xbf0ebf35,0xbf0ebf35,0x3f55bf35,0x3f7bbec4,0x3e483f6d,0x3e483f6d,0xbf7b3ec4,0x3e95bf80,0x3f750000,0x3ef13f35,0xbf623f35,
0xbf463f55,0xbf22bf0e,0x3dc9bf7b,0x3f7fbe48,0x3f7fbec4,0x3dc93f6d,0xbf223f6d,0xbf46bec4,0xbf62be48,0x3ef1bf7b,0x3f75bf0e,0x3e953f55,
0xbec43f80,0xbf6d0000,0x3ec4bf80,0x3f6d0000,0x3f6dbf35,0x3ec43f35,0xbf6d3f35,0xbec4bf35,0xbf6d0000,0x3ec4bf80,0x3f6d0000,0xbec43f80,
0x3ec43f35,0xbf6d3f35,0xbec4bf35,0x3f6dbf35,0x3ef1bf80,0x3f620000,0xbf753f35,0xbe95bf35,0xbf7f3f0e,0xbdc9bf55,0x3f463e48,0xbf223f7b,
0x3f223ec4,0xbf463f6d,0x3dc9bf6d,0x3f7fbec4,0x3e95bf7b,0x3f75be48,0xbf623f55,0xbef1bf0e,0xbf0e3f80,0xbf550000,0x3f550000,0xbf0e3f80,
0x3f7bbec4,0xbe483f6d,0x3e48bf6d,0x3f7bbec4,0xbe48bf35,0x3f7bbf35,0xbf7b3f35,0xbe48bf35,0xbf553f6d,0xbf0ebec4,0x3f0e3ec4,0xbf553f6d,
0x3f22bf80,0x3f460000,0xbdc9bf35,0x3f7fbf35,0xbf623e48,0x3ef1bf7b,0xbf753f55,0xbe95bf0e,0xbe953f6d,0xbf753ec4,0x3ef13ec4,0xbf623f6d,
0x3f7fbf0e,0xbdc93f55,0x3f46bf7b,0x3f223e48,0xbf353f80,0xbf350000,0xbf353f80,0xbf350000,0x3f350000,0xbf353f80,0x3f350000,0xbf353f80,
0x3f35bf80,0x3f350000,0x3f35bf80,0x3f350000,0xbf350000,0x3f35bf80,0xbf350000,0x3f35bf80,0x3f46bf80,0x3f220000,0x3f7fbf35,0xbdc93f35,
0xbef1be48,0x3f62bf7b,0x3e95bf55,0x3f75bf0e,0xbf753f6d,0xbe95bec4,0xbf623ec4,0x3ef1bf6d,0x3dc93f0e,0xbf7f3f55,0xbf223f7b,0xbf463e48,
0xbf553f80,0xbf0e0000,0xbf0e0000,0x3f55bf80,0x3e483ec4,0xbf7b3f6d,0xbf7b3f6d,0xbe48bec4,0x3f7bbf35,0xbe483f35,0xbe483f35,0xbf7b3f35,
0x3f0ebf6d,0x3f55bec4,0x3f55bec4,0xbf0e3f6d,0x3f62bf80,0x3ef10000,0xbe953f35,0xbf753f35,0x3dc9bf0e,0x3f7fbf55,0x3f22be48,0xbf463f7b,
0xbf463ec4,0x3f22bf6d,0x3f7fbf6d,0x3dc93ec4,0xbf753f7b,0xbe95be48,0x3ef1bf55,0x3f62bf0e,0xbf6d3f80,0xbec40000,0x3f6dbf80,0x3ec40000,
0xbec43f35,0xbf6d3f35,0x3ec4bf35,0x3f6dbf35,0x3ec40000,0xbf6d3f80,0xbec40000,0x3f6dbf80,0x3f6dbf35,0xbec43f35,0xbf6d3f35,0x3ec4bf35,
0x3f75bf80,0x3e950000,0xbf623f35,0x3ef1bf35,0x3f22bf55,0x3f46bf0e,0xbf7f3f7b,0xbdc9be48,0x3dc9bec4,0x3f7fbf6d,0xbf463f6d,0xbf223ec4,
0xbef13e48,0x3f62bf7b,0xbe953f0e,0xbf753f55,0xbf7b3f80,0xbe480000,0x3e480000,0xbf7b3f80,0xbf553f6d,0xbf0e3ec4,0x3f0ebec4,0xbf553f6d,
0xbf0e3f35,0xbf553f35,0x3f55bf35,0xbf0e3f35,0xbe483ec4,0xbf7b3f6d,0x3f7bbf6d,0xbe483ec4,0x3f7fbf80,0x3dc90000,0x3f22bf35,0x3f46bf35,
0x3f75bf7b,0x3e95be48,0x3ef1bf0e,0x3f62bf55,0x3f62bf6d,0x3ef1bec4,0x3e95bec4,0x3f75bf6d,0x3f46bf55,0x3f22bf0e,0x3dc9be48,0x3f7fbf7b,
0x3f803f80,0xbf803f80,0x3f803f80,0xbf803f80,0x3f803f80,0xbf803f80,0x3f803f80,0xbf803f80,0x3f803f80,0xbf803f80,0x3f803f80,0xbf803f80,
0x3f803f80,0xbf803f80,0x3f803f80,0xbf803f80,0x3dc90000,0x3f7f3f80,0x3f463f35,0x3f223f35,0x3e953e48,0x3f753f7b,0x3f623f55,0x3ef13f0e,
0x3ef13ec4,0x3f623f6d,0x3f753f6d,0x3e953ec4,0x3f223f0e,0x3f463f55,0x3f7f3f7b,0x3dc93e48,0xbf7bbf80,0x3e480000,0x3e480000,0x3f7b3f80,
0xbf55bf6d,0x3f0e3ec4,0x3f0e3ec4,0x3f553f6d,0xbf0ebf35,0x3f553f35,0x3f553f35,0x3f0e3f35,0xbe48bec4,0x3f7b3f6d,0x3f7b3f6d,0x3e483ec4,
0xbe950000,0xbf75bf80,0xbef1bf35,0x3f623f35,0xbf46bf0e,0xbf22bf55,0x3dc9be48,0x3f7f3f7b,0xbf7fbf6d,0xbdc9bec4,0x3f223ec4,0x3f463f6d,
0xbf62bf7b,0x3ef13e48,0x3f753f55,0x3e953f0e,0x3f6d3f80,0xbec40000,0xbf6dbf80,0x3ec40000,0x3ec43f35,0xbf6dbf35,0xbec4bf35,0x3f6d3f35,
0xbec40000,0xbf6dbf80,0x3ec40000,0x3f6d3f80,0xbf6dbf35,0xbec4bf35,0x3f6d3f35,0x3ec43f35,0x3ef10000,0x3f623f80,0xbf75bf35,0xbe95bf35,
0x3f7f3f55,0x3dc93f0e,0xbf46bf7b,0x3f223e48,0x3f223f6d,0xbf46bec4,0x3dc9bec4,0x3f7f3f6d,0xbe953e48,0xbf75bf7b,0x3f623f0e,0x3ef13f55,
0xbf55bf80,0x3f0e0000,0xbf0e0000,0xbf55bf80,0x3e48bec4,0x3f7b3f6d,0xbf7bbf6d,0x3e48bec4,0x3f7b3f35,0x3e483f35,0xbe48bf35,0x3f7b3f35,
0x3f0e3f6d,0xbf55bec4,0x3f553ec4,0x3f0e3f6d,0xbf220000,0xbf46bf80,0x3dc93f35,0xbf7fbf35,0xbf62bf7b,0x3ef1be48,0xbf75bf0e,0xbe95bf55,
0x3e95bec4,0x3f753f6d,0xbef1bf6d,0x3f623ec4,0x3f7f3f55,0xbdc93f0e,0x3f463e48,0x3f223f7b,0x3f353f80,0xbf350000,0x3f353f80,0xbf350000,
0xbf350000,0xbf35bf80,0xbf350000,0xbf35bf80,0xbf35bf80,0x3f350000,0xbf35bf80,0x3f350000,0x3f350000,0x3f353f80,0x3f350000,0x3f353f80,
0x3f460000,0x3f223f80,0x3f7f3f35,0xbdc93f35,0x3ef13f7b,0xbf62be48,0xbe953f0e,0xbf75bf55,0xbf75bec4,0xbe95bf6d,0xbf62bf6d,0x3ef1bec4,
0xbdc9bf55,0x3f7f3f0e,0x3f22be48,0x3f463f7b,0xbf0ebf80,0x3f550000,0x3f550000,0x3f0e3f80,0x3f7b3ec4,0x3e483f6d,0x3e483f6d,0xbf7bbec4,
0xbe483f35,0xbf7bbf35,0xbf7bbf35,0x3e48bf35,0xbf55bf6d,0x3f0ebec4,0x3f0ebec4,0x3f553f6d,0xbf620000,0xbef1bf80,0x3e95bf35,0x3f753f35,
0x3dc9bf55,0x3f7f3f0e,0x3f223f7b,0xbf463e48,0x3f463f6d,0xbf223ec4,0xbf7fbec4,0xbdc9bf6d,0xbf75be48,0xbe95bf7b,0x3ef1bf0e,0x3f623f55,
0x3ec43f80,0xbf6d0000,0xbec4bf80,0x3f6d0000,0xbf6dbf35,0x3ec4bf35,0x3f6d3f35,0xbec43f35,0x3f6d0000,0x3ec43f80,0xbf6d0000,0xbec4bf80,
0xbec43f35,0xbf6dbf35,0x3ec4bf35,0x3f6d3f35,0x3f750000,0x3e953f80,0xbf62bf35,0x3ef1bf35,0xbf223f0e,0xbf46bf55,0x3f7f3e48,0x3dc93f7b,
0x3dc9bf6d,0x3f7f3ec4,0xbf463ec4,0xbf22bf6d,0x3ef13f7b,0xbf623e48,0x3e95bf55,0x3f753f0e,0xbe48bf80,0x3f7b0000,0xbf7b0000,0xbe48bf80,
0x3f0e3f6d,0xbf553ec4,0x3f55bec4,0x3f0e3f6d,0xbf55bf35,0x3f0ebf35,0xbf0e3f35,0xbf55bf35,0x3f7b3ec4,0xbe483f6d,0x3e48bf6d,0x3f7b3ec4,
0xbf7f0000,0xbdc9bf80,0xbf223f35,0xbf46bf35,0x3f75be48,0x3e953f7b,0x3ef1bf55,0x3f623f0e,0xbf623ec4,0xbef1bf6d,0xbe953f6d,0xbf75bec4,
0x3f46bf0e,0x3f223f55,0x3dc9bf7b,0x3f7f3e48,0x3f80,0xbf800000,0x3f80,0xbf800000,0xbf80,0x3f800000,0xbf80,0x3f800000,
0x3f80,0xbf800000,0x3f80,0xbf800000,0xbf80,0x3f800000,0xbf80,0x3f800000,0x3f7f0000,0xbdc93f80,0x3f223f35,0xbf463f35,
0xbf75be48,0x3e95bf7b,0xbef1bf55,0x3f62bf0e,0x3f623ec4,0xbef13f6d,0x3e953f6d,0xbf753ec4,0xbf46bf0e,0x3f22bf55,0xbdc9bf7b,0x3f7fbe48,
0x3e48bf80,0x3f7b0000,0x3f7b0000,0xbe483f80,0xbf0e3f6d,0xbf55bec4,0xbf55bec4,0x3f0ebf6d,0x3f55bf35,0x3f0e3f35,0x3f0e3f35,0xbf553f35,
0xbf7b3ec4,0xbe48bf6d,0xbe48bf6d,0x3f7bbec4,0xbf750000,0x3e95bf80,0x3f62bf35,0x3ef13f35,0x3f223f0e,0xbf463f55,0xbf7f3e48,0x3dc9bf7b,
0xbdc9bf6d,0x3f7fbec4,0x3f463ec4,0xbf223f6d,0xbef13f7b,0xbf62be48,0xbe95bf55,0x3f75bf0e,0xbec43f80,0xbf6d0000,0x3ec4bf80,0x3f6d0000,
0x3f6dbf35,0x3ec43f35,0xbf6d3f35,0xbec4bf35,0xbf6d0000,0x3ec4bf80,0x3f6d0000,0xbec43f80,0x3ec43f35,0xbf6d3f35,0xbec4bf35,0x3f6dbf35,
0x3f620000,0xbef13f80,0xbe95bf35,0x3f75bf35,0xbdc9bf55,0x3f7fbf0e,0xbf223f7b,0xbf46be48,0xbf463f6d,0xbf22bec4,0x3f7fbec4,0xbdc93f6d,
0x3f75be48,0xbe953f7b,0xbef1bf0e,0x3f62bf55,0x3f0ebf80,0x3f550000,0xbf550000,0x3f0ebf80,0xbf7b3ec4,0x3e48bf6d,0xbe483f6d,0xbf7b3ec4,
0x3e483f35,0xbf7b3f35,0x3f7bbf35,0x3e483f35,0x3f55bf6d,0x3f0e3ec4,0xbf0ebec4,0x3f55bf6d,0xbf460000,0x3f22bf80,0xbf7f3f35,0xbdc9bf35,
0xbef13f7b,0xbf623e48,0x3e953f0e,0xbf753f55,0x3f75bec4,0xbe953f6d,0x3f62bf6d,0x3ef13ec4,0x3dc9bf55,0x3f7fbf0e,0xbf22be48,0x3f46bf7b,
0xbf353f80,0xbf350000,0xbf353f80,0xbf350000,0x3f350000,0xbf353f80,0x3f350000,0xbf353f80,0x3f35bf80,0x3f350000,0x3f35bf80,0x3f350000,
0xbf350000,0x3f35bf80,0xbf350000,0x3f35bf80,0x3f220000,0xbf463f80,0xbdc93f35,0xbf7f3f35,0x3f62bf7b,0x3ef13e48,0x3f75bf0e,0xbe953f55,
0xbe95bec4,0x3f75bf6d,0x3ef1bf6d,0x3f62bec4,0xbf7f3f55,0xbdc9bf0e,0xbf463e48,0x3f22bf7b,0x3f55bf80,0x3f0e0000,0x3f0e0000,0xbf553f80,
0xbe48bec4,0x3f7bbf6d,0x3f7bbf6d,0x3e483ec4,0xbf7b3f35,0x3e48bf35,0x3e48bf35,0x3f7bbf35,0xbf0e3f6d,0xbf553ec4,0xbf553ec4,0x3f0ebf6d,
0xbef10000,0x3f62bf80,0x3f75bf35,0xbe953f35,0xbf7f3f55,0x3dc9bf0e,0x3f46bf7b,0x3f22be48,0xbf223f6d,0xbf463ec4,0xbdc9bec4,0x3f7fbf6d,
0x3e953e48,0xbf753f7b,0xbf623f0e,0x3ef1bf55,0xbf6d3f80,0xbec40000,0x3f6dbf80,0x3ec40000,0xbec43f35,0xbf6d3f35,0x3ec4bf35,0x3f6dbf35,
0x3ec40000,0xbf6d3f80,0xbec40000,0x3f6dbf80,0x3f6dbf35,0xbec43f35,0xbf6d3f35,0x3ec4bf35,0x3e950000,0xbf753f80,0x3ef1bf35,0x3f62bf35,
0x3f46bf0e,0xbf223f55,0xbdc9be48,0x3f7fbf7b,0x3f7fbf6d,0xbdc93ec4,0xbf223ec4,0x3f46bf6d,0x3f62bf7b,0x3ef1be48,0xbf753f55,0x3e95bf0e,
0x3f7bbf80,0x3e480000,0xbe480000,0x3f7bbf80,0x3f55bf6d,0x3f0ebec4,0xbf0e3ec4,0x3f55bf6d,0x3f0ebf35,0x3f55bf35,0xbf553f35,0x3f0ebf35,
0x3e48bec4,0x3f7bbf6d,0xbf7b3f6d,0x3e48bec4,0xbdc90000,0x3f7fbf80,0xbf463f35,0x3f22bf35,0xbe953e48,0x3f75bf7b,0xbf623f55,0x3ef1bf0e,
0xbef13ec4,0x3f62bf6d,0xbf753f6d,0x3e95bec4,0xbf223f0e,0x3f46bf55,0xbf7f3f7b,0x3dc9be48,0x40003f80,0x3fb53f80,0x3f80,0xbfb53f80,
0x40004000,0xbfb50000,0x0,0xbfb5c000,0x40004000,0xbfb5c000,0x0,0x3fb50000,0x40004000,0x3fb50000,0x0,0x3fb54000,
0x3fff3f80,0x3fa23f80,0xbe49bf80,0xbfc6bf80,0x3ff53ffb,0xbfe2bec8,0xbf15bec8,0xbf71bffb,0x3fe23fed,0xbf15bfed,0xbf71bf44,0x3ff53f44,
0x3fc63fd5,0x3fff3f8e,0xbfa2bf8e,0x3e493fd5,0x3ffb3f80,0x3f8e3f80,0xbec83f80,0xbfd53f80,0x3fd53fed,0xbffbbf44,0xbf8ebf44,0xbec8bfed,
0x3f8e3fb5,0x3ec8bfb5,0xbfd5bfb5,0x3ffb3fb5,0x3ec83f44,0x3fd53fed,0xbffbbfed,0xbf8e3f44,0x3ff53f80,0x3f713f80,0xbf15bf80,0xbfe2bf80,
0x3fa23fd5,0xbfffbf8e,0xbfc6bf8e,0x3e49bfd5,0x3e493f44,0x3fa2bf44,0xbfffbfed,0x3fc63fed,0xbf71bec8,0x3f153ffb,0xbfe2bffb,0xbff5bec8,
0x3fed3f80,0x3f443f80,0xbf443f80,0xbfed3f80,0x3f443fb5,0xbfedbfb5,0xbfedbfb5,0x3f44bfb5,0xbf440000,0x3fed0000,0xbfedc000,0x3f444000,
0xbfedbfb5,0xbf443fb5,0xbf44bfb5,0xbfedbfb5,0x3fe23f80,0x3f153f80,0xbf71bf80,0xbff5bf80,0x3e493f8e,0xbfc6bfd5,0xbfffbfd5,0x3fa2bf8e,
0xbfc6bf44,0x3fff3f44,0xbfa2bfed,0xbe493fed,0xbff5bffb,0xbfe23ec8,0x3f15bec8,0xbf71bffb,0x3fd53f80,0x3ec83f80,0xbf8e3f80,0xbffb3f80,
0xbec83f44,0xbf8ebfed,0xbffbbfed,0x3fd5bf44,0xbffbbfb5,0x3fd53fb5,0xbec8bfb5,0xbf8e3fb5,0xbf8ebfed,0xbffbbf44,0x3fd53f44,0x3ec8bfed,
0x3fc63f80,0x3e493f80,0xbfa2bf80,0xbfffbf80,0xbf713ec8,0xbf15bffb,0xbfe2bffb,0x3ff5bec8,0xbff5bfed,0x3f713fed,0x3f15bf44,0xbfe23f44,
0x3e49bf8e,0xbfa2bfd5,0x3fff3fd5,0x3fc6bf8e,0x3f80,0xbfb53f80,0xc0003f80,0xbfb53f80,0xc000,0x3fb50000,0x40000000,0xbfb54000,
0x4000,0x3fb5c000,0xc0000000,0x3fb50000,0xc000,0xbfb50000,0x40000000,0x3fb5c000,0xbe493f80,0xbfc63f80,0xbfffbf80,0xbfa2bf80,
0x3f15bffb,0x3f713ec8,0x3ff53ec8,0xbfe23ffb,0xbf713fed,0x3ff5bfed,0xbfe2bf44,0x3f153f44,0x3fa2bfd5,0xbe49bf8e,0x3fc63f8e,0x3fffbfd5,
0xbec83f80,0xbfd53f80,0xbffb3f80,0xbf8e3f80,0x3f8ebfed,0x3ec83f44,0x3fd53f44,0xbffb3fed,0xbfd53fb5,0x3ffbbfb5,0xbf8ebfb5,0xbec83fb5,
0x3ffbbf44,0x3f8ebfed,0x3ec83fed,0x3fd5bf44,0xbf153f80,0xbfe23f80,0xbff5bf80,0xbf71bf80,0x3fc6bfd5,0xbe493f8e,0x3fa23f8e,0xbfff3fd5,
0xbfff3f44,0x3fc6bf44,0xbe49bfed,0xbfa23fed,0x3fe23ec8,0x3ff5bffb,0xbf713ffb,0x3f153ec8,0xbf443f80,0xbfed3f80,0xbfed3f80,0xbf443f80,
0x3fedbfb5,0xbf443fb5,0x3f443fb5,0xbfed3fb5,0xbfed0000,0x3f440000,0x3f44c000,0xbfed4000,0x3f443fb5,0x3fedbfb5,0xbfed3fb5,0xbf443fb5,
0xbf713f80,0xbff53f80,0xbfe2bf80,0xbf15bf80,0x3fffbf8e,0xbfa23fd5,0x3e493fd5,0xbfc63f8e,0xbfa2bf44,0xbe493f44,0x3fc6bfed,0xbfff3fed,
0xbf153ffb,0x3f71bec8,0xbff53ec8,0xbfe23ffb,0xbf8e3f80,0xbffb3f80,0xbfd53f80,0xbec83f80,0x3ffbbf44,0xbfd53fed,0xbec83fed,0xbf8e3f44,
0xbec8bfb5,0xbf8e3fb5,0x3ffbbfb5,0xbfd53fb5,0xbfd53fed,0xbec83f44,0xbf8ebf44,0xbffb3fed,0xbfa23f80,0xbfff3f80,0xbfc6bf80,0xbe49bf80,
0x3fe2bec8,0xbff53ffb,0xbf713ffb,0xbf153ec8,0x3f15bfed,0xbfe23fed,0x3ff5bf44,0xbf713f44,0xbfff3f8e,0xbfc63fd5,0x3e49bfd5,0xbfa23f8e,
0xc0003f80,0xbfb53f80,0x3f80,0x3fb53f80,0xc0004000,0x3fb50000,0x0,0x3fb5c000,0xc0004000,0x3fb5c000,0x0,0xbfb50000,
0xc0004000,0xbfb50000,0x0,0xbfb54000,0xbfff3f80,0xbfa23f80,0x3e49bf80,0x3fc6bf80,0xbff53ffb,0x3fe2bec8,0x3f15bec8,0x3f71bffb,
0xbfe23fed,0x3f15bfed,0x3f71bf44,0xbff53f44,0xbfc63fd5,0xbfff3f8e,0x3fa2bf8e,0xbe493fd5,0xbffb3f80,0xbf8e3f80,0x3ec83f80,0x3fd53f80,
0xbfd53fed,0x3ffbbf44,0x3f8ebf44,0x3ec8bfed,0xbf8e3fb5,0xbec8bfb5,0x3fd5bfb5,0xbffb3fb5,0xbec83f44,0xbfd53fed,0x3ffbbfed,0x3f8e3f44,
0xbff53f80,0xbf713f80,0x3f15bf80,0x3fe2bf80,0xbfa23fd5,0x3fffbf8e,0x3fc6bf8e,0xbe49bfd5,0xbe493f44,0xbfa2bf44,0x3fffbfed,0xbfc63fed,
0x3f71bec8,0xbf153ffb,0x3fe2bffb,0x3ff5bec8,0xbfed3f80,0xbf443f80,0x3f443f80,0x3fed3f80,0xbf443fb5,0x3fedbfb5,0x3fedbfb5,0xbf44bfb5,
0x3f440000,0xbfed0000,0x3fedc000,0xbf444000,0x3fedbfb5,0x3f443fb5,0x3f44bfb5,0x3fedbfb5,0xbfe23f80,0xbf153f80,0x3f71bf80,0x3ff5bf80,
0xbe493f8e,0x3fc6bfd5,0x3fffbfd5,0xbfa2bf8e,0x3fc6bf44,0xbfff3f44,0x3fa2bfed,0x3e493fed,0x3ff5bffb,0x3fe23ec8,0xbf15bec8,0x3f71bffb,
0xbfd53f80,0xbec83f80,0x3f8e3f80,0x3ffb3f80,0x3ec83f44,0x3f8ebfed,0x3ffbbfed,0xbfd5bf44,0x3ffbbfb5,0xbfd53fb5,0x3ec8bfb5,0x3f8e3fb5,
0x3f8ebfed,0x3ffbbf44,0xbfd53f44,0xbec8bfed,0xbfc63f80,0xbe493f80,0x3fa2bf80,0x3fffbf80,0x3f713ec8,0x3f15bffb,0x3fe2bffb,0xbff5bec8,
0x3ff5bfed,0xbf713fed,0xbf15bf44,0x3fe23f44,0xbe49bf8e,0x3fa2bfd5,0xbfff3fd5,0xbfc6bf8e,0x3f80,0x3fb53f80,0x40003f80,0x3fb53f80,
0xc000,0xbfb50000,0xc0000000,0x3fb54000,0x4000,0xbfb5c000,0x40000000,0xbfb50000,0xc000,0x3fb50000,0xc0000000,0xbfb5c000,
0x3e493f80,0x3fc63f80,0x3fffbf80,0x3fa2bf80,0xbf15bffb,0xbf713ec8,0xbff53ec8,0x3fe23ffb,0x3f713fed,0xbff5bfed,0x3fe2bf44,0xbf153f44,
0xbfa2bfd5,0x3e49bf8e,0xbfc63f8e,0xbfffbfd5,0x3ec83f80,0x3fd53f80,0x3ffb3f80,0x3f8e3f80,0xbf8ebfed,0xbec83f44,0xbfd53f44,0x3ffb3fed,
0x3fd53fb5,0xbffbbfb5,0x3f8ebfb5,0x3ec83fb5,0xbffbbf44,0xbf8ebfed,0xbec83fed,0xbfd5bf44,0x3f153f80,0x3fe23f80,0x3ff5bf80,0x3f71bf80,
0xbfc6bfd5,0x3e493f8e,0xbfa23f8e,0x3fff3fd5,0x3fff3f44,0xbfc6bf44,0x3e49bfed,0x3fa23fed,0xbfe23ec8,0xbff5bffb,0x3f713ffb,0xbf153ec8,
0x3f443f80,0x3fed3f80,0x3fed3f80,0x3f443f80,0xbfedbfb5,0x3f443fb5,0xbf443fb5,0x3fed3fb5,0x3fed0000,0xbf440000,0xbf44c000,0x3fed4000,
0xbf443fb5,0xbfedbfb5,0x3fed3fb5,0x3f443fb5,0x3f713f80,0x3ff53f80,0x3fe2bf80,0x3f15bf80,0xbfffbf8e,0x3fa23fd5,0xbe493fd5,0x3fc63f8e,
0x3fa2bf44,0x3e493f44,0xbfc6bfed,0x3fff3fed,0x3f153ffb,0xbf71bec8,0x3ff53ec8,0x3fe23ffb,0x3f8e3f80,0x3ffb3f80,0x3fd53f80,0x3ec83f80,
0xbffbbf44,0x3fd53fed,0x3ec83fed,0x3f8e3f44,0x3ec8bfb5,0x3f8e3fb5,0xbffbbfb5,0x3fd53fb5,0x3fd53fed,0x3ec83f44,0x3f8ebf44,0x3ffb3fed,
0x3fa23f80,0x3fff3f80,0x3fc6bf80,0x3e49bf80,0xbfe2bec8,0x3ff53ffb,0x3f713ffb,0x3f153ec8,0xbf15bfed,0x3fe23fed,0xbff5bf44,0x3f713f44,
0x3fff3f8e,0x3fc63fd5,0xbe49bfd5,0x3fa23f8e,0x40004000,0x3fb54000,0x0,0xbfb50000,0x40004000,0xbfb50000,0x0,0xbfb5c000,
0x40004000,0xbfb5c000,0x0,0x3fb50000,0x40004000,0x3fb50000,0x0,0x3fb54000,0x3fa23fb5,0xbe493fb5,0xbfc6bfb5,0xbfffbfb5,
0x3f713f8e,0xbff5bfd5,0xbfe2bfd5,0x3f15bf8e,0x3f153f44,0x3f71bf44,0xbff5bfed,0x3fe23fed,0x3e493ec8,0x3fc63ffb,0xbfffbffb,0xbfa23ec8,
0xbec80000,0xbfd50000,0xbffbc000,0xbf8ec000,0xbf8ebf44,0xbec8bfed,0xbfd5bfed,0x3ffb3f44,0xbfd5bfb5,0x3ffb3fb5,0xbf8ebfb5,0xbec83fb5,
0xbffbbfed,0xbf8e3f44,0xbec8bf44,0xbfd5bfed,0xbfe2bfb5,0xbff5bfb5,0xbf71bfb5,0x3f15bfb5,0xbfffbffb,0x3fc6bec8,0x3e49bec8,0x3fa23ffb,
0xbfc6bfed,0x3e493fed,0x3fa23f44,0xbfffbf44,0xbf15bf8e,0xbfe2bfd5,0x3ff53fd5,0x3f71bf8e,0xbfedc000,0xbf44c000,0x3f440000,0x3fed0000,
0xbf44bfb5,0x3fed3fb5,0x3fed3fb5,0xbf443fb5,0x3f440000,0xbfed0000,0x3fed4000,0xbf44c000,0x3fed3fb5,0x3f44bfb5,0x3f443fb5,0x3fed3fb5,
0xbf15bfb5,0x3f71bfb5,0x3ff53fb5,0x3fe23fb5,0x3fa23ec8,0x3e493ffb,0x3fc63ffb,0xbfffbec8,0x3fff3fed,0xbfa2bfed,0xbe493f44,0x3fc6bf44,
0x3f713fd5,0x3ff53f8e,0xbfe2bf8e,0xbf153fd5,0x3f8e0000,0x3ffb0000,0x3fd54000,0x3ec84000,0x3ffb3fed,0xbfd53f44,0xbec83f44,0xbf8ebfed,
0x3ec83fb5,0x3f8ebfb5,0xbffbbfb5,0x3fd53fb5,0xbfd5bf44,0xbec83fed,0xbf8ebfed,0xbffbbf44,0x3fff3fb5,0x3fc63fb5,0x3e493fb5,0xbfa23fb5,
0x3f153fd5,0xbfe2bf8e,0xbff5bf8e,0x3f71bfd5,0xbfe2bf44,0x3ff53f44,0xbf71bfed,0xbf153fed,0xbfa2bffb,0xbfffbec8,0x3fc63ec8,0x3e49bffb,
0x4000,0xbfb54000,0xc0000000,0xbfb50000,0xc000,0x3fb50000,0x40000000,0xbfb54000,0x4000,0x3fb5c000,0xc0000000,0x3fb50000,
0xc000,0xbfb50000,0x40000000,0x3fb5c000,0xbfc63fb5,0xbfff3fb5,0xbfa2bfb5,0x3e49bfb5,0x3fe2bf8e,0xbf153fd5,0x3f713fd5,0xbff53f8e,
0xbff53f44,0x3fe2bf44,0xbf15bfed,0xbf713fed,0x3fffbec8,0x3fa2bffb,0x3e493ffb,0x3fc6bec8,0xbffb0000,0xbf8e0000,0x3ec8c000,0x3fd5c000,
0x3fd53f44,0xbffb3fed,0xbf8e3fed,0xbec8bf44,0xbf8ebfb5,0xbec83fb5,0x3fd5bfb5,0xbffb3fb5,0x3ec83fed,0x3fd5bf44,0xbffb3f44,0xbf8e3fed,
0xbf71bfb5,0x3f15bfb5,0x3fe2bfb5,0x3ff5bfb5,0xbe493ffb,0xbfa23ec8,0xbfff3ec8,0x3fc6bffb,0x3fa2bfed,0xbfff3fed,0x3fc63f44,0xbe49bf44,
0xbff53f8e,0xbf713fd5,0xbf15bfd5,0xbfe23f8e,0x3f44c000,0x3fedc000,0x3fed0000,0x3f440000,0xbfed3fb5,0x3f44bfb5,0xbf44bfb5,0x3fedbfb5,
0x3fed0000,0xbf440000,0xbf444000,0x3fedc000,0xbf44bfb5,0xbfed3fb5,0x3fedbfb5,0x3f44bfb5,0x3ff5bfb5,0x3fe2bfb5,0x3f153fb5,0xbf713fb5,
0xbfc6bec8,0x3fffbffb,0x3fa2bffb,0x3e493ec8,0xbe493fed,0x3fc6bfed,0xbfff3f44,0x3fa2bf44,0x3fe2bfd5,0x3f15bf8e,0x3f713f8e,0x3ff5bfd5,
0x3fd50000,0x3ec80000,0xbf8e4000,0xbffb4000,0x3ec8bfed,0x3f8ebf44,0x3ffbbf44,0xbfd53fed,0xbffb3fb5,0x3fd5bfb5,0xbec8bfb5,0xbf8e3fb5,
0x3f8e3f44,0x3ffbbfed,0xbfd53fed,0xbec83f44,0x3e493fb5,0xbfa23fb5,0xbfff3fb5,0xbfc63fb5,0x3ff5bfd5,0xbf713f8e,0x3f153f8e,0xbfe23fd5,
0xbf71bf44,0xbf153f44,0x3fe2bfed,0xbff53fed,0xbfc63ffb,0xbe493ec8,0xbfa2bec8,0xbfff3ffb,0xc0004000,0xbfb54000,0x0,0x3fb50000,
0xc0004000,0x3fb50000,0x0,0x3fb5c000,0xc0004000,0x3fb5c000,0x0,0xbfb50000,0xc0004000,0xbfb50000,0x0,0xbfb54000,
0xbfa23fb5,0x3e493fb5,0x3fc6bfb5,0x3fffbfb5,0xbf713f8e,0x3ff5bfd5,0x3fe2bfd5,0xbf15bf8e,0xbf153f44,0xbf71bf44,0x3ff5bfed,0xbfe23fed,
0xbe493ec8,0xbfc63ffb,0x3fffbffb,0x3fa23ec8,0x3ec80000,0x3fd50000,0x3ffbc000,0x3f8ec000,0x3f8ebf44,0x3ec8bfed,0x3fd5bfed,0xbffb3f44,
0x3fd5bfb5,0xbffb3fb5,0x3f8ebfb5,0x3ec83fb5,0x3ffbbfed,0x3f8e3f44,0x3ec8bf44,0x3fd5bfed,0x3fe2bfb5,0x3ff5bfb5,0x3f71bfb5,0xbf15bfb5,
0x3fffbffb,0xbfc6bec8,0xbe49bec8,0xbfa23ffb,0x3fc6bfed,0xbe493fed,0xbfa23f44,0x3fffbf44,0x3f15bf8e,0x3fe2bfd5,0xbff53fd5,0xbf71bf8e,
0x3fedc000,0x3f44c000,0xbf440000,0xbfed0000,0x3f44bfb5,0xbfed3fb5,0xbfed3fb5,0x3f443fb5,0xbf440000,0x3fed0000,0xbfed4000,0x3f44c000,
0xbfed3fb5,0xbf44bfb5,0xbf443fb5,0xbfed3fb5,0x3f15bfb5,0xbf71bfb5,0xbff53fb5,0xbfe23fb5,0xbfa23ec8,0xbe493ffb,0xbfc63ffb,0x3fffbec8,
0xbfff3fed,0x3fa2bfed,0x3e493f44,0xbfc6bf44,0xbf713fd5,0xbff53f8e,0x3fe2bf8e,0x3f153fd5,0xbf8e0000,0xbffb0000,0xbfd54000,0xbec84000,
0xbffb3fed,0x3fd53f44,0x3ec83f44,0x3f8ebfed,0xbec83fb5,0xbf8ebfb5,0x3ffbbfb5,0xbfd53fb5,0x3fd5bf44,0x3ec83fed,0x3f8ebfed,0x3ffbbf44,
0xbfff3fb5,0xbfc63fb5,0xbe493fb5,0x3fa23fb5,0xbf153fd5,0x3fe2bf8e,0x3ff5bf8e,0xbf71bfd5,0x3fe2bf44,0xbff53f44,0x3f71bfed,0x3f153fed,
0x3fa2bffb,0x3fffbec8,0xbfc63ec8,0xbe49bffb,0x4000,0x3fb54000,0x40000000,0x3fb50000,0xc000,0xbfb50000,0xc0000000,0x3fb54000,
0x4000,0xbfb5c000,0x40000000,0xbfb50000,0xc000,0x3fb50000,0xc0000000,0xbfb5c000,0x3fc63fb5,0x3fff3fb5,0x3fa2bfb5,0xbe49bfb5,
0xbfe2bf8e,0x3f153fd5,0xbf713fd5,0x3ff53f8e,0x3ff53f44,0xbfe2bf44,0x3f15bfed,0x3f713fed,0xbfffbec8,0xbfa2bffb,0xbe493ffb,0xbfc6bec8,
0x3ffb0000,0x3f8e0000,0xbec8c000,0xbfd5c000,0xbfd53f44,0x3ffb3fed,0x3f8e3fed,0x3ec8bf44,0x3f8ebfb5,0x3ec83fb5,0xbfd5bfb5,0x3ffb3fb5,
0xbec83fed,0xbfd5bf44,0x3ffb3f44,0x3f8e3fed,0x3f71bfb5,0xbf15bfb5,0xbfe2bfb5,0xbff5bfb5,0x3e493ffb,0x3fa23ec8,0x3fff3ec8,0xbfc6bffb,
0xbfa2bfed,0x3fff3fed,0xbfc63f44,0x3e49bf44,0x3ff53f8e,0x3f713fd5,0x3f15bfd5,0x3fe23f8e,0xbf44c000,0xbfedc000,0xbfed0000,0xbf440000,
0x3fed3fb5,0xbf44bfb5,0x3f44bfb5,0xbfedbfb5,0xbfed0000,0x3f440000,0x3f444000,0xbfedc000,0x3f44bfb5,0x3fed3fb5,0xbfedbfb5,0xbf44bfb5,
0xbff5bfb5,0xbfe2bfb5,0xbf153fb5,0x3f713fb5,0x3fc6bec8,0xbfffbffb,0xbfa2bffb,0xbe493ec8,0x3e493fed,0xbfc6bfed,0x3fff3f44,0xbfa2bf44,
0xbfe2bfd5,0xbf15bf8e,0xbf713f8e,0xbff5bfd5,0xbfd50000,0xbec80000,0x3f8e4000,0x3ffb4000,0xbec8bfed,0xbf8ebf44,0xbffbbf44,0x3fd53fed,
0x3ffb3fb5,0xbfd5bfb5,0x3ec8bfb5,0x3f8e3fb5,0xbf8e3f44,0xbffbbfed,0x3fd53fed,0x3ec83f44,0xbe493fb5,0x3fa23fb5,0x3fff3fb5,0x3fc63fb5,
0xbff5bfd5,0x3f713f8e,0xbf153f8e,0x3fe23fd5,0x3f71bf44,0x3f153f44,0xbfe2bfed,0x3ff53fed,0x3fc63ffb,0x3e493ec8,0x3fa2bec8,0x3fff3ffb,
0x40004000,0x3fb54000,0x0,0xbfb50000,0x40004000,0xbfb50000,0x0,0xbfb5c000,0x40004000,0xbfb5c000,0x0,0x3fb50000,
0x40004000,0x3fb50000,0x0,0x3fb54000,0xbe490000,0xbfc60000,0xbfffc000,0xbfa2c000,0xbf15bec8,0xbf71bffb,0xbff5bffb,0x3fe23ec8,
0xbf71bf44,0x3ff53f44,0xbfe2bfed,0x3f153fed,0xbfa2bf8e,0x3e493fd5,0xbfc6bfd5,0xbfffbf8e,0xbffbc000,0xbf8ec000,0x3ec80000,0x3fd50000,
0xbfd5bfed,0x3ffb3f44,0x3f8e3f44,0x3ec83fed,0xbf8ebfb5,0xbec83fb5,0x3fd53fb5,0xbffbbfb5,0xbec8bf44,0xbfd5bfed,0x3ffb3fed,0x3f8ebf44,
0x3f150000,0x3fe20000,0x3ff54000,0x3f714000,0x3fc63f8e,0xbe493fd5,0x3fa23fd5,0xbfffbf8e,0x3fff3fed,0xbfc6bfed,0x3e493f44,0x3fa2bf44,
0x3fe23ffb,0x3ff53ec8,0xbf71bec8,0x3f153ffb,0x3fed4000,0x3f444000,0xbf440000,0xbfed0000,0x3f443fb5,0xbfedbfb5,0xbfedbfb5,0x3f44bfb5,
0xbf440000,0x3fed0000,0xbfedc000,0x3f444000,0xbfedbfb5,0xbf443fb5,0xbf44bfb5,0xbfedbfb5,0xbf710000,0xbff50000,0xbfe2c000,0xbf15c000,
0xbfffbfd5,0x3fa2bf8e,0xbe49bf8e,0x3fc63fd5,0xbfa2bfed,0xbe493fed,0x3fc63f44,0xbfffbf44,0x3f15bec8,0xbf71bffb,0x3ff53ffb,0x3fe2bec8,
0xbfd5c000,0xbec8c000,0x3f8e0000,0x3ffb0000,0x3ec8bf44,0x3f8e3fed,0x3ffb3fed,0xbfd53f44,0x3ffb3fb5,0xbfd5bfb5,0x3ec83fb5,0x3f8ebfb5,
0x3f8e3fed,0x3ffb3f44,0xbfd5bf44,0xbec83fed,0x3fa20000,0x3fff0000,0x3fc64000,0x3e494000,0x3fe23ffb,0xbff53ec8,0xbf713ec8,0xbf15bffb,
0xbf153f44,0x3fe2bf44,0xbff5bfed,0x3f713fed,0xbfffbfd5,0xbfc63f8e,0x3e49bf8e,0xbfa2bfd5,0x4000,0xbfb54000,0xc0000000,0xbfb50000,
0xc000,0x3fb50000,0x40000000,0xbfb54000,0x4000,0x3fb5c000,0xc0000000,0x3fb50000,0xc000,0xbfb50000,0x40000000,0x3fb5c000,
0xbfff0000,0xbfa20000,0x3e49c000,0x3fc6c000,0x3ff53ec8,0xbfe23ffb,0xbf153ffb,0xbf71bec8,0xbfe2bf44,0x3f153f44,0x3f71bfed,0xbff53fed,
0x3fc63f8e,0x3fffbfd5,0xbfa23fd5,0x3e493f8e,0x3ec8c000,0x3fd5c000,0x3ffb0000,0x3f8e0000,0xbf8e3fed,0xbec8bf44,0xbfd5bf44,0x3ffbbfed,
0x3fd5bfb5,0xbffb3fb5,0x3f8e3fb5,0x3ec8bfb5,0xbffb3f44,0xbf8e3fed,0xbec8bfed,0xbfd53f44,0x3ff50000,0x3f710000,0xbf154000,0xbfe24000,
0xbfa2bf8e,0x3fffbfd5,0x3fc6bfd5,0xbe493f8e,0x3e493fed,0x3fa2bfed,0xbfff3f44,0x3fc6bf44,0x3f71bffb,0xbf15bec8,0x3fe23ec8,0x3ff5bffb,
0xbf444000,0xbfed4000,0xbfed0000,0xbf440000,0x3fedbfb5,0xbf443fb5,0x3f443fb5,0xbfed3fb5,0xbfed0000,0x3f440000,0x3f44c000,0xbfed4000,
0x3f443fb5,0x3fedbfb5,0xbfed3fb5,0xbf443fb5,0xbfe20000,0xbf150000,0x3f71c000,0x3ff5c000,0x3e493fd5,0xbfc63f8e,0xbfff3f8e,0x3fa2bfd5,
0x3fc6bfed,0xbfff3fed,0x3fa23f44,0x3e49bf44,0xbff53ec8,0xbfe23ffb,0x3f15bffb,0xbf713ec8,0x3f8ec000,0x3ffbc000,0x3fd50000,0x3ec80000,
0xbffb3f44,0x3fd5bfed,0x3ec8bfed,0x3f8ebf44,0x3ec83fb5,0x3f8ebfb5,0xbffb3fb5,0x3fd5bfb5,0x3fd5bfed,0x3ec8bf44,0x3f8e3f44,0x3ffbbfed,
0x3fc60000,0x3e490000,0xbfa24000,0xbfff4000,0x3f71bffb,0x3f15bec8,0x3fe2bec8,0xbff53ffb,0xbff53f44,0x3f71bf44,0x3f15bfed,0xbfe23fed,
0xbe493fd5,0x3fa2bf8e,0xbfff3f8e,0xbfc63fd5,0xc0004000,0xbfb54000,0x0,0x3fb50000,0xc0004000,0x3fb50000,0x0,0x3fb5c000,
0xc0004000,0x3fb5c000,0x0,0xbfb50000,0xc0004000,0xbfb50000,0x0,0xbfb54000,0x3e490000,0x3fc60000,0x3fffc000,0x3fa2c000,
0x3f15bec8,0x3f71bffb,0x3ff5bffb,0xbfe23ec8,0x3f71bf44,0xbff53f44,0x3fe2bfed,0xbf153fed,0x3fa2bf8e,0xbe493fd5,0x3fc6bfd5,0x3fffbf8e,
0x3ffbc000,0x3f8ec000,0xbec80000,0xbfd50000,0x3fd5bfed,0xbffb3f44,0xbf8e3f44,0xbec83fed,0x3f8ebfb5,0x3ec83fb5,0xbfd53fb5,0x3ffbbfb5,
0x3ec8bf44,0x3fd5bfed,0xbffb3fed,0xbf8ebf44,0xbf150000,0xbfe20000,0xbff54000,0xbf714000,0xbfc63f8e,0x3e493fd5,0xbfa23fd5,0x3fffbf8e,
0xbfff3fed,0x3fc6bfed,0xbe493f44,0xbfa2bf44,0xbfe23ffb,0xbff53ec8,0x3f71bec8,0xbf153ffb,0xbfed4000,0xbf444000,0x3f440000,0x3fed0000,
0xbf443fb5,0x3fedbfb5,0x3fedbfb5,0xbf44bfb5,0x3f440000,0xbfed0000,0x3fedc000,0xbf444000,0x3fedbfb5,0x3f443fb5,0x3f44bfb5,0x3fedbfb5,
0x3f710000,0x3ff50000,0x3fe2c000,0x3f15c000,0x3fffbfd5,0xbfa2bf8e,0x3e49bf8e,0xbfc63fd5,0x3fa2bfed,0x3e493fed,0xbfc63f44,0x3fffbf44,
0xbf15bec8,0x3f71bffb,0xbff53ffb,0xbfe2bec8,0x3fd5c000,0x3ec8c000,0xbf8e0000,0xbffb0000,0xbec8bf44,0xbf8e3fed,0xbffb3fed,0x3fd53f44,
0xbffb3fb5,0x3fd5bfb5,0xbec83fb5,0xbf8ebfb5,0xbf8e3fed,0xbffb3f44,0x3fd5bf44,0x3ec83fed,0xbfa20000,0xbfff0000,0xbfc64000,0xbe494000,
0xbfe23ffb,0x3ff53ec8,0x3f713ec8,0x3f15bffb,0x3f153f44,0xbfe2bf44,0x3ff5bfed,0xbf713fed,0x3fffbfd5,0x3fc63f8e,0xbe49bf8e,0x3fa2bfd5,
0x4000,0x3fb54000,0x40000000,0x3fb50000,0xc000,0xbfb50000,0xc0000000,0x3fb54000,0x4000,0xbfb5c000,0x40000000,0xbfb50000,
0xc000,0x3fb50000,0xc0000000,0xbfb5c000,0x3fff0000,0x3fa20000,0xbe49c000,0xbfc6c000,0xbff53ec8,0x3fe23ffb,0x3f153ffb,0x3f71bec8,
0x3fe2bf44,0xbf153f44,0xbf71bfed,0x3ff53fed,0xbfc63f8e,0xbfffbfd5,0x3fa23fd5,0xbe493f8e,0xbec8c000,0xbfd5c000,0xbffb0000,0xbf8e0000,
0x3f8e3fed,0x3ec8bf44,0x3fd5bf44,0xbffbbfed,0xbfd5bfb5,0x3ffb3fb5,0xbf8e3fb5,0xbec8bfb5,0x3ffb3f44,0x3f8e3fed,0x3ec8bfed,0x3fd53f44,
0xbff50000,0xbf710000,0x3f154000,0x3fe24000,0x3fa2bf8e,0xbfffbfd5,0xbfc6bfd5,0x3e493f8e,0xbe493fed,0xbfa2bfed,0x3fff3f44,0xbfc6bf44,
0xbf71bffb,0x3f15bec8,0xbfe23ec8,0xbff5bffb,0x3f444000,0x3fed4000,0x3fed0000,0x3f440000,0xbfedbfb5,0x3f443fb5,0xbf443fb5,0x3fed3fb5,
0x3fed0000,0xbf440000,0xbf44c000,0x3fed4000,0xbf443fb5,0xbfedbfb5,0x3fed3fb5,0x3f443fb5,0x3fe20000,0x3f150000,0xbf71c000,0xbff5c000,
0xbe493fd5,0x3fc63f8e,0x3fff3f8e,0xbfa2bfd5,0xbfc6bfed,0x3fff3fed,0xbfa23f44,0xbe49bf44,0x3ff53ec8,0x3fe23ffb,0xbf15bffb,0x3f713ec8,
0xbf8ec000,0xbffbc000,0xbfd50000,0xbec80000,0x3ffb3f44,0xbfd5bfed,0xbec8bfed,0xbf8ebf44,0xbec83fb5,0xbf8ebfb5,0x3ffb3fb5,0xbfd5bfb5,
0xbfd5bfed,0xbec8bf44,0xbf8e3f44,0xbffbbfed,0xbfc60000,0xbe490000,0x3fa24000,0x3fff4000,0xbf71bffb,0xbf15bec8,0xbfe2bec8,0x3ff53ffb,
0x3ff53f44,0xbf71bf44,0xbf15bfed,0x3fe23fed,0x3e493fd5,0xbfa2bf8e,0x3fff3f8e,0x3fc63fd5,0x40004000,0x3fb54000,0x0,0xbfb50000,
0x40004000,0xbfb50000,0x0,0xbfb5c000,0x40004000,0xbfb5c000,0x0,0x3fb50000,0x40004000,0x3fb50000,0x0,0x3fb54000,
0xbfc6bfb5,0xbfffbfb5,0xbfa2bfb5,0x3e49bfb5,0xbfe2bfd5,0x3f15bf8e,0xbf71bf8e,0x3ff53fd5,0xbff5bfed,0x3fe23fed,0xbf15bf44,0xbf713f44,
0xbfffbffb,0xbfa23ec8,0xbe49bec8,0xbfc6bffb,0x3ec80000,0x3fd50000,0x3ffb4000,0x3f8e4000,0x3f8e3f44,0x3ec83fed,0x3fd53fed,0xbffbbf44,
0x3fd53fb5,0xbffbbfb5,0x3f8e3fb5,0x3ec8bfb5,0x3ffb3fed,0x3f8ebf44,0x3ec83f44,0x3fd53fed,0x3f713fb5,0xbf153fb5,0xbfe2bfb5,0xbff5bfb5,
0xbe493ec8,0xbfa2bffb,0xbfffbffb,0x3fc6bec8,0xbfa2bf44,0x3fff3f44,0xbfc6bfed,0x3e493fed,0xbff5bfd5,0xbf713f8e,0xbf15bf8e,0xbfe2bfd5,
0xbfedc000,0xbf44c000,0x3f440000,0x3fed0000,0xbf44bfb5,0x3fed3fb5,0x3fed3fb5,0xbf443fb5,0x3f440000,0xbfed0000,0x3fed4000,0xbf44c000,
0x3fed3fb5,0x3f44bfb5,0x3f443fb5,0x3fed3fb5,0x3ff53fb5,0x3fe23fb5,0x3f153fb5,0xbf713fb5,0x3fc63ffb,0xbfffbec8,0xbfa2bec8,0xbe49bffb,
0xbe493f44,0x3fc6bf44,0xbfffbfed,0x3fa23fed,0xbfe2bf8e,0xbf153fd5,0xbf71bfd5,0xbff5bf8e,0xbf8e0000,0xbffb0000,0xbfd5c000,0xbec8c000,
0xbffbbfed,0x3fd5bf44,0x3ec8bf44,0x3f8e3fed,0xbec8bfb5,0xbf8e3fb5,0x3ffb3fb5,0xbfd5bfb5,0x3fd53f44,0x3ec8bfed,0x3f8e3fed,0x3ffb3f44,
0xbe49bfb5,0x3fa2bfb5,0x3fff3fb5,0x3fc63fb5,0x3ff53f8e,0xbf713fd5,0x3f153fd5,0xbfe2bf8e,0x3f713fed,0x3f15bfed,0xbfe2bf44,0x3ff53f44,
0xbfc6bec8,0xbe493ffb,0xbfa2bffb,0xbfffbec8,0x4000,0xbfb54000,0xc0000000,0xbfb50000,0xc000,0x3fb50000,0x40000000,0xbfb54000,
0x4000,0x3fb5c000,0xc0000000,0x3fb50000,0xc000,0xbfb50000,0x40000000,0x3fb5c000,0xbfa2bfb5,0x3e49bfb5,0x3fc6bfb5,0x3fffbfb5,
0x3f713fd5,0xbff53f8e,0xbfe23f8e,0x3f15bfd5,0xbf15bfed,0xbf713fed,0x3ff5bf44,0xbfe23f44,0x3e493ffb,0x3fc6bec8,0xbfff3ec8,0xbfa23ffb,
0x3ffb0000,0x3f8e0000,0xbec84000,0xbfd54000,0xbfd5bf44,0x3ffbbfed,0x3f8ebfed,0x3ec83f44,0x3f8e3fb5,0x3ec8bfb5,0xbfd53fb5,0x3ffbbfb5,
0xbec8bfed,0xbfd53f44,0x3ffbbf44,0x3f8ebfed,0xbfe23fb5,0xbff53fb5,0xbf71bfb5,0x3f15bfb5,0x3fffbec8,0xbfc63ffb,0xbe493ffb,0xbfa23ec8,
0xbfc6bf44,0x3e493f44,0x3fa2bfed,0xbfff3fed,0x3f153fd5,0x3fe2bf8e,0xbff53f8e,0xbf713fd5,0x3f44c000,0x3fedc000,0x3fed0000,0x3f440000,
0xbfed3fb5,0x3f44bfb5,0xbf44bfb5,0x3fedbfb5,0x3fed0000,0xbf440000,0xbf444000,0x3fedc000,0xbf44bfb5,0xbfed3fb5,0x3fedbfb5,0x3f44bfb5,
0x3f153fb5,0xbf713fb5,0xbff53fb5,0xbfe23fb5,0x3fa2bffb,0x3e493ec8,0x3fc63ec8,0xbfff3ffb,0xbfff3f44,0x3fa2bf44,0x3e49bfed,0xbfc63fed,
0x3f713f8e,0x3ff5bfd5,0xbfe23fd5,0xbf153f8e,0xbfd50000,0xbec80000,0x3f8ec000,0x3ffbc000,0xbec83fed,0xbf8e3f44,0xbffb3f44,0x3fd5bfed,
0x3ffbbfb5,0xbfd53fb5,0x3ec83fb5,0x3f8ebfb5,0xbf8ebf44,0xbffb3fed,0x3fd5bfed,0x3ec8bf44,0x3fffbfb5,0x3fc6bfb5,0x3e493fb5,0xbfa23fb5,
0xbf15bf8e,0x3fe2bfd5,0x3ff5bfd5,0xbf713f8e,0xbfe23fed,0x3ff5bfed,0xbf71bf44,0xbf153f44,0x3fa23ec8,0x3fffbffb,0xbfc63ffb,0xbe493ec8,
0xc0004000,0xbfb54000,0x0,0x3fb50000,0xc0004000,0x3fb50000,0x0,0x3fb5c000,0xc0004000,0x3fb5c000,0x0,0xbfb50000,
0xc0004000,0xbfb50000,0x0,0xbfb54000,0x3fc6bfb5,0x3fffbfb5,0x3fa2bfb5,0xbe49bfb5,0x3fe2bfd5,0xbf15bf8e,0x3f71bf8e,0xbff53fd5,
0x3ff5bfed,0xbfe23fed,0x3f15bf44,0x3f713f44,0x3fffbffb,0x3fa23ec8,0x3e49bec8,0x3fc6bffb,0xbec80000,0xbfd50000,0xbffb4000,0xbf8e4000,
0xbf8e3f44,0xbec83fed,0xbfd53fed,0x3ffbbf44,0xbfd53fb5,0x3ffbbfb5,0xbf8e3fb5,0xbec8bfb5,0xbffb3fed,0xbf8ebf44,0xbec83f44,0xbfd53fed,
0xbf713fb5,0x3f153fb5,0x3fe2bfb5,0x3ff5bfb5,0x3e493ec8,0x3fa2bffb,0x3fffbffb,0xbfc6bec8,0x3fa2bf44,0xbfff3f44,0x3fc6bfed,0xbe493fed,
0x3ff5bfd5,0x3f713f8e,0x3f15bf8e,0x3fe2bfd5,0x3fedc000,0x3f44c000,0xbf440000,0xbfed0000,0x3f44bfb5,0xbfed3fb5,0xbfed3fb5,0x3f443fb5,
0xbf440000,0x3fed0000,0xbfed4000,0x3f44c000,0xbfed3fb5,0xbf44bfb5,0xbf443fb5,0xbfed3fb5,0xbff53fb5,0xbfe23fb5,0xbf153fb5,0x3f713fb5,
0xbfc63ffb,0x3fffbec8,0x3fa2bec8,0x3e49bffb,0x3e493f44,0xbfc6bf44,0x3fffbfed,0xbfa23fed,0x3fe2bf8e,0x3f153fd5,0x3f71bfd5,0x3ff5bf8e,
0x3f8e0000,0x3ffb0000,0x3fd5c000,0x3ec8c000,0x3ffbbfed,0xbfd5bf44,0xbec8bf44,0xbf8e3fed,0x3ec8bfb5,0x3f8e3fb5,0xbffb3fb5,0x3fd5bfb5,
0xbfd53f44,0xbec8bfed,0xbf8e3fed,0xbffb3f44,0x3e49bfb5,0xbfa2bfb5,0xbfff3fb5,0xbfc63fb5,0xbff53f8e,0x3f713fd5,0xbf153fd5,0x3fe2bf8e,
0xbf713fed,0xbf15bfed,0x3fe2bf44,0xbff53f44,0x3fc6bec8,0x3e493ffb,0x3fa2bffb,0x3fffbec8,0x4000,0x3fb54000,0x40000000,0x3fb50000,
0xc000,0xbfb50000,0xc0000000,0x3fb54000,0x4000,0xbfb5c000,0x40000000,0xbfb50000,0xc000,0x3fb50000,0xc0000000,0xbfb5c000,
0x3fa2bfb5,0xbe49bfb5,0xbfc6bfb5,0xbfffbfb5,0xbf713fd5,0x3ff53f8e,0x3fe23f8e,0xbf15bfd5,0x3f15bfed,0x3f713fed,0xbff5bf44,0x3fe23f44,
0xbe493ffb,0xbfc6bec8,0x3fff3ec8,0x3fa23ffb,0xbffb0000,0xbf8e0000,0x3ec84000,0x3fd54000,0x3fd5bf44,0xbffbbfed,0xbf8ebfed,0xbec83f44,
0xbf8e3fb5,0xbec8bfb5,0x3fd53fb5,0xbffbbfb5,0x3ec8bfed,0x3fd53f44,0xbffbbf44,0xbf8ebfed,0x3fe23fb5,0x3ff53fb5,0x3f71bfb5,0xbf15bfb5,
0xbfffbec8,0x3fc63ffb,0x3e493ffb,0x3fa23ec8,0x3fc6bf44,0xbe493f44,0xbfa2bfed,0x3fff3fed,0xbf153fd5,0xbfe2bf8e,0x3ff53f8e,0x3f713fd5,
0xbf44c000,0xbfedc000,0xbfed0000,0xbf440000,0x3fed3fb5,0xbf44bfb5,0x3f44bfb5,0xbfedbfb5,0xbfed0000,0x3f440000,0x3f444000,0xbfedc000,
0x3f44bfb5,0x3fed3fb5,0xbfedbfb5,0xbf44bfb5,0xbf153fb5,0x3f713fb5,0x3ff53fb5,0x3fe23fb5,0xbfa2bffb,0xbe493ec8,0xbfc63ec8,0x3fff3ffb,
0x3fff3f44,0xbfa2bf44,0xbe49bfed,0x3fc63fed,0xbf713f8e,0xbff5bfd5,0x3fe23fd5,0x3f153f8e,0x3fd50000,0x3ec80000,0xbf8ec000,0xbffbc000,
0x3ec83fed,0x3f8e3f44,0x3ffb3f44,0xbfd5bfed,0xbffbbfb5,0x3fd53fb5,0xbec83fb5,0xbf8ebfb5,0x3f8ebf44,0x3ffb3fed,0xbfd5bfed,0xbec8bf44,
0xbfffbfb5,0xbfc6bfb5,0xbe493fb5,0x3fa23fb5,0x3f15bf8e,0xbfe2bfd5,0xbff5bfd5,0x3f713f8e,0x3fe23fed,0xbff5bfed,0x3f71bf44,0x3f153f44,
0xbfa23ec8,0xbfffbffb,0x3fc63ffb,0x3e493ec8,0x80003f80,0x3f800000,0x80003f80,0x3f800000,0x80003f80,0x3f800000,0x80003f80,0x3f800000,
0x80003f80,0x3f800000,0x80003f80,0x3f800000,0x80003f80,0x3f800000,0x80003f80,0x3f800000,0x80003f80,0x3f800000,0x8000bf80,0xbf800000,
0x3f353f35,0x3f35bf35,0xbf35bf35,0xbf353f35,0x3f800000,0xbf80,0xbf800000,0x3f80,0x3f35bf35,0xbf35bf35,0xbf353f35,0x3f353f35,
0x80003f80,0x3f800000,0x80003f80,0x3f800000,0x3f800000,0xbf80,0x3f800000,0xbf80,0x8000bf80,0xbf800000,0x8000bf80,0xbf800000,
0xbf800000,0x3f80,0xbf800000,0x3f80,0x80003f80,0x3f800000,0x8000bf80,0xbf800000,0x3f35bf35,0xbf35bf35,0xbf353f35,0x3f353f35,
0xbf800000,0x3f80,0x3f800000,0xbf80,0x3f353f35,0x3f35bf35,0xbf35bf35,0xbf353f35,0x80003f80,0x3f800000,0x80003f80,0x3f800000,
0x8000bf80,0xbf800000,0x8000bf80,0xbf800000,0x80003f80,0x3f800000,0x80003f80,0x3f800000,0x8000bf80,0xbf800000,0x8000bf80,0xbf800000,
0x80003f80,0x3f800000,0x8000bf80,0xbf800000,0xbf35bf35,0xbf353f35,0x3f353f35,0x3f35bf35,0x3f800000,0xbf80,0xbf800000,0x3f80,
0xbf353f35,0x3f353f35,0x3f35bf35,0xbf35bf35,0x80003f80,0x3f800000,0x80003f80,0x3f800000,0xbf800000,0x3f80,0xbf800000,0x3f80,
0x8000bf80,0xbf800000,0x8000bf80,0xbf800000,0x3f800000,0xbf80,0x3f800000,0xbf80,0x80003f80,0x3f800000,0x8000bf80,0xbf800000,
0xbf353f35,0x3f353f35,0x3f35bf35,0xbf35bf35,0xbf800000,0x3f80,0x3f800000,0xbf80,0xbf35bf35,0xbf353f35,0x3f353f35,0x3f35bf35,
0x3f803f80,0x80008000,0x80008000,0xbf80bf80,0x3f803f80,0x80008000,0x80008000,0xbf80bf80,0x3f803f80,0x80008000,0x80008000,0xbf80bf80,
0x3f803f80,0x80008000,0x80008000,0xbf80bf80,0x3f353f80,0x3f358000,0x3f358000,0xbf35bf80,0xbf350000,0x3f353f80,0x3f353f80,0x3f358000,
0xbf35bf80,0xbf358000,0xbf358000,0x3f353f80,0x3f350000,0xbf35bf80,0xbf35bf80,0xbf358000,0x3f80,0x3f808000,0x3f808000,0x8000bf80,
0xbf80,0xbf808000,0xbf808000,0x80003f80,0x3f80,0x3f808000,0x3f808000,0x8000bf80,0xbf80,0xbf808000,0xbf808000,0x80003f80,
0xbf353f80,0x3f358000,0x3f358000,0x3f35bf80,0x3f350000,0x3f35bf80,0x3f35bf80,0xbf358000,0x3f35bf80,0xbf358000,0xbf358000,0xbf353f80,
0xbf350000,0xbf353f80,0xbf353f80,0x3f358000,0xbf803f80,0x80008000,0x80008000,0x3f80bf80,0xbf803f80,0x80008000,0x80008000,0x3f80bf80,
0xbf803f80,0x80008000,0x80008000,0x3f80bf80,0xbf803f80,0x80008000,0x80008000,0x3f80bf80,0xbf353f80,0xbf358000,0xbf358000,0x3f35bf80,
0x3f350000,0xbf353f80,0xbf353f80,0xbf358000,0x3f35bf80,0x3f358000,0x3f358000,0xbf353f80,0xbf350000,0x3f35bf80,0x3f35bf80,0x3f358000,
0x3f80,0xbf808000,0xbf808000,0x8000bf80,0xbf80,0x3f808000,0x3f808000,0x80003f80,0x3f80,0xbf808000,0xbf808000,0x8000bf80,
0xbf80,0x3f808000,0x3f808000,0x80003f80,0x3f353f80,0xbf358000,0xbf358000,0xbf35bf80,0xbf350000,0xbf35bf80,0xbf35bf80,0x3f358000,
0xbf35bf80,0x3f358000,0x3f358000,0x3f353f80,0x3f350000,0x3f353f80,0x3f353f80,0xbf358000,0x3f800000,0x0,0x3f800000,0x0,
0x3f800000,0x0,0x3f800000,0x0,0x3f800000,0x0,0x3f800000,0x0,0x3f800000,0x0,0x3f800000,0x0,
0x3f800000,0x0,0x3f7fb10f,0xbd48fb30,0x3f7ec46d,0xbdc8bd36,0x3f7d3aac,0xbe164083,0x3f7b14be,0xbe47c5c2,0x3f7853f8,0xbe78cfcc,
0x3f74fa0b,0xbe94a031,0x3f710908,0xbeac7cd4,0x3f800000,0x0,0x3f7ec46d,0xbdc8bd36,0x3f7b14be,0xbe47c5c2,0x3f74fa0b,0xbe94a031,
0x3f6c835e,0xbec3ef15,0x3f61c598,0xbef15aea,0x3f54db31,0xbf0e39da,0x3f45e403,0xbf226799,0x3f800000,0x0,0x3f7d3aac,0xbe164083,
0x3f74fa0b,0xbe94a031,0x3f676bd8,0xbedae880,0x3f54db31,0xbf0e39da,0x3f3daef9,0xbf2beb4a,0x3f226799,0xbf45e403,0x3f039c3d,0xbf5b941a,
0x3f800000,0x0,0x3f7b14be,0xbe47c5c2,0x3f6c835e,0xbec3ef15,0x3f54db31,0xbf0e39da,0x3f3504f3,0xbf3504f3,0x3f0e39da,0xbf54db31,
0x3ec3ef15,0xbf6c835e,0x3e47c5c2,0xbf7b14be,0x3f800000,0x0,0x3f7853f8,0xbe78cfcc,0x3f61c598,0xbef15aea,0x3f3daef9,0xbf2beb4a,
0x3f0e39da,0xbf54db31,0x3eac7cd4,0xbf710908,0x3dc8bd36,0xbf7ec46d,0xbe164083,0xbf7d3aac,0x3f800000,0x0,0x3f74fa0b,0xbe94a031,
0x3f54db31,0xbf0e39da,0x3f226799,0xbf45e403,0x3ec3ef15,0xbf6c835e,0x3dc8bd36,0xbf7ec46d,0xbe47c5c2,0xbf7b14be,0xbef15aea,0xbf61c598,
0x3f800000,0x0,0x3f710908,0xbeac7cd4,0x3f45e403,0xbf226799,0x3f039c3d,0xbf5b941a,0x3e47c5c2,0xbf7b14be,0xbe164083,0xbf7d3aac,
0xbef15aea,0xbf61c598,0xbf3daef9,0xbf2beb4a,0x3f800000,0x0,0x3f800000,0x0,0x3f800000,0x0,0x3f800000,0x0,
0x3f800000,0x0,0x3f800000,0x0,0x3f800000,0x0,0x3f800000,0x0,0x3f6c835e,0xbec3ef15,0x3f676bd8,0xbedae880,
0x3f61c598,0xbef15aea,0x3f5b941a,0xbf039c3d,0x3f54db31,0xbf0e39da,0x3f4d9f02,0xbf187fc0,0x3f45e403,0xbf226799,0x3f3daef9,0xbf2beb4a,
0x3f3504f3,0xbf3504f3,0x3f226799,0xbf45e403,0x3f0e39da,0xbf54db31,0x3ef15aea,0xbf61c598,0x3ec3ef15,0xbf6c835e,0x3e94a031,0xbf74fa0b,
0x3e47c5c2,0xbf7b14be,0x3dc8bd36,0xbf7ec46d,0x3ec3ef15,0xbf6c835e,0x3e78cfcc,0xbf7853f8,0x3dc8bd36,0xbf7ec46d,0xbd48fb30,0xbf7fb10f,
0xbe47c5c2,0xbf7b14be,0xbeac7cd4,0xbf710908,0xbef15aea,0xbf61c598,0xbf187fc0,0xbf4d9f02,0x0,0xbf800000,0xbe47c5c2,0xbf7b14be,
0xbec3ef15,0xbf6c835e,0xbf0e39da,0xbf54db31,0xbf3504f3,0xbf3504f3,0xbf54db31,0xbf0e39da,0xbf6c835e,0xbec3ef15,0xbf7b14be,0xbe47c5c2,
0xbec3ef15,0xbf6c835e,0xbf187fc0,0xbf4d9f02,0xbf45e403,0xbf226799,0xbf676bd8,0xbedae880,0xbf7b14be,0xbe47c5c2,0xbf7fb10f,0x3d48fb30,
0xbf74fa0b,0x3e94a031,0xbf5b941a,0x3f039c3d,0xbf3504f3,0xbf3504f3,0xbf61c598,0xbef15aea,0xbf7b14be,0xbe47c5c2,0xbf7ec46d,0x3dc8bd36,
0xbf6c835e,0x3ec3ef15,0xbf45e403,0x3f226799,0xbf0e39da,0x3f54db31,0xbe94a031,0x3f74fa0b,0xbf6c835e,0xbec3ef15,0xbf7fb10f,0xbd48fb30,
0xbf74fa0b,0x3e94a031,0xbf4d9f02,0x3f187fc0,0xbf0e39da,0x3f54db31,0xbe78cfcc,0x3f7853f8,0x3dc8bd36,0x3f7ec46d,0x3edae880,0x3f676bd8,
0x80003f80,0x3f800000,0x3f800000,0xbf80,0x3ec43f6d,0x3f6dbec4,0x3f6dbec4,0xbec4bf6d,0x3f353f35,0x3f35bf35,0x3f35bf35,0xbf35bf35,
0x3f6d3ec4,0x3ec4bf6d,0x3ec4bf6d,0xbf6dbec4,0x80003f80,0x3f800000,0xbf800000,0x3f80,0x3f6d3ec4,0x3ec4bf6d,0xbec43f6d,0x3f6d3ec4,
0x3f35bf35,0xbf35bf35,0x3f353f35,0x3f35bf35,0xbec4bf6d,0xbf6d3ec4,0x3f6dbec4,0xbec4bf6d,0x80003f80,0x3f800000,0x3f800000,0xbf80,
0x3f6dbec4,0xbec4bf6d,0xbec4bf6d,0xbf6d3ec4,0xbf35bf35,0xbf353f35,0xbf353f35,0x3f353f35,0xbec43f6d,0x3f6d3ec4,0x3f6d3ec4,0x3ec4bf6d,
0x80003f80,0x3f800000,0xbf800000,0x3f80,0x3ec4bf6d,0xbf6dbec4,0x3f6d3ec4,0x3ec4bf6d,0xbf353f35,0x3f353f35,0xbf35bf35,0xbf353f35,
0x3f6dbec4,0xbec4bf6d,0x3ec43f6d,0x3f6dbec4,0x80003f80,0x3f800000,0x3f800000,0xbf80,0xbec4bf6d,0xbf6d3ec4,0xbf6d3ec4,0x3ec43f6d,
0x3f353f35,0x3f35bf35,0x3f35bf35,0xbf35bf35,0xbf6dbec4,0xbec43f6d,0xbec43f6d,0x3f6d3ec4,0x80003f80,0x3f800000,0xbf800000,0x3f80,
0xbf6dbec4,0xbec43f6d,0x3ec4bf6d,0xbf6dbec4,0x3f35bf35,0xbf35bf35,0x3f353f35,0x3f35bf35,0x3ec43f6d,0x3f6dbec4,0xbf6d3ec4,0x3ec43f6d,
0x80003f80,0x3f800000,0x3f800000,0xbf80,0xbf6d3ec4,0x3ec43f6d,0x3ec43f6d,0x3f6dbec4,0xbf35bf35,0xbf353f35,0xbf353f35,0x3f353f35,
0x3ec4bf6d,0xbf6dbec4,0xbf6dbec4,0xbec43f6d,0x80003f80,0x3f800000,0xbf800000,0x3f80,0xbec43f6d,0x3f6d3ec4,0xbf6dbec4,0xbec43f6d,
0xbf353f35,0x3f353f35,0xbf35bf35,0xbf353f35,0xbf6d3ec4,0x3ec43f6d,0xbec4bf6d,0xbf6d3ec4,0x3f803f80,0x80008000,0x80008000,0xbf80bf80,
0x3f803f80,0x80008000,0x80008000,0xbf80bf80,0x3f803f80,0x80008000,0x80008000,0xbf80bf80,0x3f803f80,0x80008000,0x80008000,0xbf80bf80,
0x3ec43f6d,0x3f6d3ec4,0x3f6d3ec4,0xbec4bf6d,0xbf6dbec4,0x3ec43f6d,0x3ec43f6d,0x3f6d3ec4,0xbec4bf6d,0xbf6dbec4,0xbf6dbec4,0x3ec43f6d,
0x3f6d3ec4,0xbec4bf6d,0xbec4bf6d,0xbf6dbec4,0xbf353f35,0x3f353f35,0x3f353f35,0x3f35bf35,0x3f35bf35,0xbf35bf35,0xbf35bf35,0xbf353f35,
0xbf353f35,0x3f353f35,0x3f353f35,0x3f35bf35,0x3f35bf35,0xbf35bf35,0xbf35bf35,0xbf353f35,0xbf6d3ec4,0xbec43f6d,0xbec43f6d,0x3f6dbec4,
0xbec43f6d,0x3f6dbec4,0x3f6dbec4,0x3ec4bf6d,0x3f6dbec4,0x3ec4bf6d,0x3ec4bf6d,0xbf6d3ec4,0x3ec4bf6d,0xbf6d3ec4,0xbf6d3ec4,0xbec43f6d,
0x0,0xbf803f80,0xbf803f80,0x80008000,0x0,0xbf803f80,0xbf803f80,0x80008000,0x0,0xbf803f80,0xbf803f80,0x80008000,
0x0,0xbf803f80,0xbf803f80,0x80008000,0x3f6dbec4,0xbec43f6d,0xbec43f6d,0xbf6d3ec4,0x3ec4bf6d,0x3f6dbec4,0x3f6dbec4,0xbec43f6d,
0xbf6d3ec4,0x3ec4bf6d,0x3ec4bf6d,0x3f6dbec4,0xbec43f6d,0xbf6d3ec4,0xbf6d3ec4,0x3ec4bf6d,0x3f35bf35,0x3f353f35,0x3f353f35,0xbf353f35,
0xbf353f35,0xbf35bf35,0xbf35bf35,0x3f35bf35,0x3f35bf35,0x3f353f35,0x3f353f35,0xbf353f35,0xbf353f35,0xbf35bf35,0xbf35bf35,0x3f35bf35,
0xbec4bf6d,0x3f6d3ec4,0x3f6d3ec4,0x3ec43f6d,0x3f6d3ec4,0x3ec43f6d,0x3ec43f6d,0xbf6dbec4,0x3ec43f6d,0xbf6dbec4,0xbf6dbec4,0xbec4bf6d,
0xbf6dbec4,0xbec4bf6d,0xbec4bf6d,0x3f6d3ec4,0x3f800000,0x0,0x3f7fec43,0xbcc90ab0,0x3f7fb10f,0xbd48fb30,0x3f7f4e6d,0xbd96a905,
0x3f7ec46d,0xbdc8bd36,0x3f7e1324,0xbdfab273,0x3f7d3aac,0xbe164083,0x3f7c3b28,0xbe2f10a2,0x3f800000,0x0,0x3f7f4e6d,0xbd96a905,
0x3f7d3aac,0xbe164083,0x3f79c79d,0xbe605c13,0x3f74fa0b,0xbe94a031,0x3f6ed89e,0xbeb8442a,0x3f676bd8,0xbedae880,0x3f5ebe05,0xbefc5d27,
0x3f800000,0x0,0x3f7e1324,0xbdfab273,0x3f7853f8,0xbe78cfcc,0x3f6ed89e,0xbeb8442a,0x3f61c598,0xbef15aea,0x3f514d3d,0xbf13682a,
0x3f3daef9,0xbf2beb4a,0x3f273656,0xbf41d870,0x3f800000,0x0,0x3f7c3b28,0xbe2f10a2,0x3f710908,0xbeac7cd4,0x3f5ebe05,0xbefc5d27,
0x3f45e403,0xbf226799,0x3f273656,0xbf41d870,0x3f039c3d,0xbf5b941a,0x3eb8442a,0xbf6ed89e,0x3f800000,0x0,0x3f79c79d,0xbe605c13,
0x3f676bd8,0xbedae880,0x3f49d112,0xbf1d7fd1,0x3f226799,0xbf45e403,0x3ee63375,0xbf64aa59,0x3e78cfcc,0xbf7853f8,0x3cc90ab0,0xbf7fec43,
0x3f800000,0x0,0x3f76ba07,0xbe888e93,0x3f5b941a,0xbf039c3d,0x3f3085bb,0xbf396842,0x3ef15aea,0xbf61c598,0x3e605c13,0xbf79c79d,
0xbd48fb30,0xbf7fb10f,0xbea09ae5,0xbf731447,0x3f800000,0x0,0x3f731447,0xbea09ae5,0x3f4d9f02,0xbf187fc0,0x3f13682a,0xbf514d3d,
0x3e94a031,0xbf74fa0b,0xbcc90ab0,0xbf7fec43,0xbeac7cd4,0xbf710908,0xbf1d7fd1,0xbf49d112,0x3f800000,0x0,0x3f6ed89e,0xbeb8442a,
0x3f3daef9,0xbf2beb4a,0x3ee63375,0xbf64aa59,0x3dc8bd36,0xbf7ec46d,0xbe888e93,0xbf76ba07,0xbf187fc0,0xbf4d9f02,0xbf584853,0xbf08f59b,
0x3f7b14be,0xbe47c5c2,0x3f79c79d,0xbe605c13,0x3f7853f8,0xbe78cfcc,0x3f76ba07,0xbe888e93,0x3f74fa0b,0xbe94a031,0x3f731447,0xbea09ae5,
0x3f710908,0xbeac7cd4,0x3f6ed89e,0xbeb8442a,0x3f54db31,0xbf0e39da,0x3f49d112,0xbf1d7fd1,0x3f3daef9,0xbf2beb4a,0x3f3085bb,0xbf396842,
0x3f226799,0xbf45e403,0x3f13682a,0xbf514d3d,0x3f039c3d,0xbf5b941a,0x3ee63375,0xbf64aa59,0x3f0e39da,0xbf54db31,0x3ee63375,0xbf64aa59,
0x3eac7cd4,0xbf710908,0x3e605c13,0xbf79c79d,0x3dc8bd36,0xbf7ec46d,0xbcc90ab0,0xbf7fec43,0xbe164083,0xbf7d3aac,0xbe888e93,0xbf76ba07,
0x3e47c5c2,0xbf7b14be,0x3cc90ab0,0xbf7fec43,0xbe164083,0xbf7d3aac,0xbea09ae5,0xbf731447,0xbef15aea,0xbf61c598,0xbf1d7fd1,0xbf49d112,
0xbf3daef9,0xbf2beb4a,0xbf584853,0xbf08f59b,0xbe47c5c2,0xbf7b14be,0xbecf7bca,0xbf6a09a7,0xbf187fc0,0xbf4d9f02,0xbf41d870,0xbf273656,
0xbf61c598,0xbef15aea,0xbf76ba07,0xbe888e93,0xbf7fb10f,0xbd48fb30,0xbf7c3b28,0x3e2f10a2,0xbf0e39da,0xbf54db31,0xbf41d870,0xbf273656,
0xbf676bd8,0xbedae880,0xbf7c3b28,0xbe2f10a2,0xbf7ec46d,0x3dc8bd36,0xbf6ed89e,0x3eb8442a,0xbf4d9f02,0x3f187fc0,0xbf1d7fd1,0x3f49d112,
0xbf54db31,0xbf0e39da,0xbf76ba07,0xbe888e93,0xbf7fb10f,0x3d48fb30,0xbf6ed89e,0x3eb8442a,0xbf45e403,0x3f226799,0xbf08f59b,0x3f584853,
0xbe78cfcc,0x3f7853f8,0x3d96a905,0x3f7f4e6d,0xbf7b14be,0xbe47c5c2,0xbf7c3b28,0x3e2f10a2,0xbf5b941a,0x3f039c3d,0xbf1d7fd1,0x3f49d112,
0xbe94a031,0x3f74fa0b,0x3d96a905,0x3f7f4e6d,0x3edae880,0x3f676bd8,0x3f396842,0x3f3085bb,0x80003f80,0x80003f80,0x80003f80,0x80003f80,
0x80003f80,0x80003f80,0x80003f80,0x80003f80,0x80003f80,0x80003f80,0x80003f80,0x80003f80,0x80003f80,0x80003f80,0x80003f80,0x80003f80,
0x3f800000,0x3f800000,0x3f800000,0x3f800000,0x3f800000,0x3f800000,0x3f800000,0x3f800000,0x3f800000,0x3f800000,0x3f800000,0x3f800000,
0x3f800000,0x3f800000,0x3f800000,0x3f800000,0x80003f80,0x3f353f35,0x80003f80,0x3f353f35,0x3f800000,0x3f35bf35,0x3f800000,0x3f35bf35,
0x8000bf80,0xbf35bf35,0x8000bf80,0xbf35bf35,0xbf800000,0xbf353f35,0xbf800000,0xbf353f35,0x3f800000,0x3f35bf35,0x3f800000,0x3f35bf35,
0xbf80,0xbf35bf35,0xbf80,0xbf35bf35,0xbf800000,0xbf353f35,0xbf800000,0xbf353f35,0x3f80,0x3f353f35,0x3f80,0x3f353f35,
0x80003f80,0x3f800000,0x80003f80,0x3f800000,0x8000bf80,0xbf800000,0x8000bf80,0xbf800000,0x80003f80,0x3f800000,0x80003f80,0x3f800000,
0x8000bf80,0xbf800000,0x8000bf80,0xbf800000,0x3f800000,0xbf80,0x3f800000,0xbf80,0xbf800000,0x3f80,0xbf800000,0x3f80,
0x3f800000,0xbf80,0x3f800000,0xbf80,0xbf800000,0x3f80,0xbf800000,0x3f80,0x80003f80,0x3f35bf35,0x80003f80,0x3f35bf35,
0xbf800000,0x3f353f35,0xbf800000,0x3f353f35,0x8000bf80,0xbf353f35,0x8000bf80,0xbf353f35,0x3f800000,0xbf35bf35,0x3f800000,0xbf35bf35,
0x3f800000,0xbf35bf35,0x3f800000,0xbf35bf35,0x3f80,0x3f35bf35,0x3f80,0x3f35bf35,0xbf800000,0x3f353f35,0xbf800000,0x3f353f35,
0xbf80,0xbf353f35,0xbf80,0xbf353f35,0x80003f80,0x3ec43f6d,0x8000bf80,0xbec4bf6d,0x3f353f35,0x3f6d3ec4,0xbf35bf35,0xbf6dbec4,
0x3f800000,0x3f6dbec4,0xbf800000,0xbf6d3ec4,0x3f35bf35,0x3ec4bf6d,0xbf353f35,0xbec43f6d,0x3f800000,0x3f6dbec4,0xbf800000,0xbf6d3ec4,
0x3f35bf35,0x3ec4bf6d,0xbf353f35,0xbec43f6d,0xbf80,0xbec4bf6d,0x3f80,0x3ec43f6d,0xbf35bf35,0xbf6dbec4,0x3f353f35,0x3f6d3ec4,
0x80003f80,0x3f6d3ec4,0x8000bf80,0xbf6dbec4,0x3f35bf35,0xbec4bf6d,0xbf353f35,0x3ec43f6d,0xbf800000,0xbec43f6d,0x3f800000,0x3ec4bf6d,
0x3f353f35,0x3f6dbec4,0xbf35bf35,0xbf6d3ec4,0x3f800000,0x3ec4bf6d,0xbf800000,0xbec43f6d,0xbf35bf35,0xbf6d3ec4,0x3f353f35,0x3f6dbec4,
0x3f80,0x3f6d3ec4,0xbf80,0xbf6dbec4,0x3f35bf35,0xbec4bf6d,0xbf353f35,0x3ec43f6d,0x80003f80,0x3f6dbec4,0x8000bf80,0xbf6d3ec4,
0xbf35bf35,0xbec43f6d,0x3f353f35,0x3ec4bf6d,0x3f800000,0xbec4bf6d,0xbf800000,0x3ec43f6d,0xbf353f35,0x3f6d3ec4,0x3f35bf35,0xbf6dbec4,
0x3f800000,0xbec4bf6d,0xbf800000,0x3ec43f6d,0xbf353f35,0x3f6d3ec4,0x3f35bf35,0xbf6dbec4,0xbf80,0xbf6d3ec4,0x3f80,0x3f6dbec4,
0x3f353f35,0x3ec4bf6d,0xbf35bf35,0xbec43f6d,0x80003f80,0x3ec4bf6d,0x8000bf80,0xbec43f6d,0xbf353f35,0x3f6dbec4,0x3f35bf35,0xbf6d3ec4,
0xbf800000,0x3f6d3ec4,0x3f800000,0xbf6dbec4,0xbf35bf35,0x3ec43f6d,0x3f353f35,0xbec4bf6d,0x3f800000,0xbf6dbec4,0xbf800000,0x3f6d3ec4,
0x3f353f35,0xbec4bf6d,0xbf35bf35,0x3ec43f6d,0x3f80,0x3ec4bf6d,0xbf80,0xbec43f6d,0xbf353f35,0x3f6dbec4,0x3f35bf35,0xbf6d3ec4,
0x80003f80,0x8000bf80,0x80003f80,0x8000bf80,0x80003f80,0x8000bf80,0x80003f80,0x8000bf80,0x80003f80,0x8000bf80,0x80003f80,0x8000bf80,
0x80003f80,0x8000bf80,0x80003f80,0x8000bf80,0x3f800000,0xbf800000,0x3f800000,0xbf800000,0x3f800000,0xbf800000,0x3f800000,0xbf800000,
0x3f800000,0xbf800000,0x3f800000,0xbf800000,0x3f800000,0xbf800000,0x3f800000,0xbf800000,0x80003f80,0xbf35bf35,0x80003f80,0xbf35bf35,
0x3f800000,0xbf353f35,0x3f800000,0xbf353f35,0x8000bf80,0x3f353f35,0x8000bf80,0x3f353f35,0xbf800000,0x3f35bf35,0xbf800000,0x3f35bf35,
0x3f800000,0xbf353f35,0x3f800000,0xbf353f35,0xbf80,0x3f353f35,0xbf80,0x3f353f35,0xbf800000,0x3f35bf35,0xbf800000,0x3f35bf35,
0x3f80,0xbf35bf35,0x3f80,0xbf35bf35,0x80003f80,0xbf800000,0x80003f80,0xbf800000,0x8000bf80,0x3f800000,0x8000bf80,0x3f800000,
0x80003f80,0xbf800000,0x80003f80,0xbf800000,0x8000bf80,0x3f800000,0x8000bf80,0x3f800000,0x3f800000,0x3f80,0x3f800000,0x3f80,
0xbf800000,0xbf80,0xbf800000,0xbf80,0x3f800000,0x3f80,0x3f800000,0x3f80,0xbf800000,0xbf80,0xbf800000,0xbf80,
0x80003f80,0xbf353f35,0x80003f80,0xbf353f35,0xbf800000,0xbf35bf35,0xbf800000,0xbf35bf35,0x8000bf80,0x3f35bf35,0x8000bf80,0x3f35bf35,
0x3f800000,0x3f353f35,0x3f800000,0x3f353f35,0x3f800000,0x3f353f35,0x3f800000,0x3f353f35,0x3f80,0xbf353f35,0x3f80,0xbf353f35,
0xbf800000,0xbf35bf35,0xbf800000,0xbf35bf35,0xbf80,0x3f35bf35,0xbf80,0x3f35bf35,0x80003f80,0xbec4bf6d,0x8000bf80,0x3ec43f6d,
0x3f353f35,0xbf6dbec4,0xbf35bf35,0x3f6d3ec4,0x3f800000,0xbf6d3ec4,0xbf800000,0x3f6dbec4,0x3f35bf35,0xbec43f6d,0xbf353f35,0x3ec4bf6d,
0x3f800000,0xbf6d3ec4,0xbf800000,0x3f6dbec4,0x3f35bf35,0xbec43f6d,0xbf353f35,0x3ec4bf6d,0xbf80,0x3ec43f6d,0x3f80,0xbec4bf6d,
0xbf35bf35,0x3f6d3ec4,0x3f353f35,0xbf6dbec4,0x80003f80,0xbf6dbec4,0x8000bf80,0x3f6d3ec4,0x3f35bf35,0x3ec43f6d,0xbf353f35,0xbec4bf6d,
0xbf800000,0x3ec4bf6d,0x3f800000,0xbec43f6d,0x3f353f35,0xbf6d3ec4,0xbf35bf35,0x3f6dbec4,0x3f800000,0xbec43f6d,0xbf800000,0x3ec4bf6d,
0xbf35bf35,0x3f6dbec4,0x3f353f35,0xbf6d3ec4,0x3f80,0xbf6dbec4,0xbf80,0x3f6d3ec4,0x3f35bf35,0x3ec43f6d,0xbf353f35,0xbec4bf6d,
0x80003f80,0xbf6d3ec4,0x8000bf80,0x3f6dbec4,0xbf35bf35,0x3ec4bf6d,0x3f353f35,0xbec43f6d,0x3f800000,0x3ec43f6d,0xbf800000,0xbec4bf6d,
0xbf353f35,0xbf6dbec4,0x3f35bf35,0x3f6d3ec4,0x3f800000,0x3ec43f6d,0xbf800000,0xbec4bf6d,0xbf353f35,0xbf6dbec4,0x3f35bf35,0x3f6d3ec4,
0xbf80,0x3f6dbec4,0x3f80,0xbf6d3ec4,0x3f353f35,0xbec43f6d,0xbf35bf35,0x3ec4bf6d,0x80003f80,0xbec43f6d,0x8000bf80,0x3ec4bf6d,
0xbf353f35,0xbf6d3ec4,0x3f35bf35,0x3f6dbec4,0xbf800000,0xbf6dbec4,0x3f800000,0x3f6d3ec4,0xbf35bf35,0xbec4bf6d,0x3f353f35,0x3ec43f6d,
0x3f800000,0x3f6d3ec4,0xbf800000,0xbf6dbec4,0x3f353f35,0x3ec43f6d,0xbf35bf35,0xbec4bf6d,0x3f80,0xbec43f6d,0xbf80,0x3ec4bf6d,
0xbf353f35,0xbf6d3ec4,0x3f35bf35,0x3f6dbec4,
};
constexpr int TB_F = 0, TB_E = 512, TB_P2 = 1024;

enum { C_EP = 0, C_Z1 = 32, C_Z2 = 96, C_H3 = 128, C_U = 160, C_TOTAL = 256 };
struct Scratch {
  unsigned cnt[C_TOTAL];
  uint32_t mod[6 * D_ + 384];
  uint32_t z1[120 * 5120];
  uint32_t z2[128 * 4800];
  uint32_t x1[S_ * D_ / 2];
  uint8_t h3[32 * 18 * 4096];
  uint8_t u[72 * D_ * 128];
  uint4 part[128 * 1152];
};
__device__ __align__(1024) Scratch g_s;

#define PF2 8
#define PF2K 16
#define HOLDA 3
#define GOAT 1
#define HOLD1 0
#define XPOS 0
#define HW bulk_commit_wait
#define NG1 4

#define FAILCNT(k) do {} while (0)
#define CK(k) do {} while (0)
#define TS(k) do {} while (0)
#define TSC(k) do {} while (0)
struct Maps { CUtensorMap w1a, w1b, w2, x1, out, z1, z2, h3, wf[4], wm; };
struct Params {
  const __nv_bfloat16 *x, *c, *wmod;
  Scratch* s;
  const uint4* tab;
  const __nv_bfloat16 *wr, *wi, *w1, *w2, *b1, *b2;
};

__device__ __forceinline__ uint32_t smem_u32(const void* p) { return (uint32_t)__cvta_generic_to_shared(p); }
__device__ __forceinline__ void mbar_init(uint32_t b, int c) { asm volatile("mbarrier.init.shared::cta.b64 [%0], %1;" ::"r"(b), "r"(c)); }
__device__ __forceinline__ void mbar_expect(uint32_t b, int bytes) { asm volatile("mbarrier.arrive.expect_tx.shared::cta.b64 _, [%0], %1;" ::"r"(b), "r"(bytes) : "memory"); }
__device__ __forceinline__ void mbar_arrive(uint32_t b) { asm volatile("mbarrier.arrive.shared::cta.b64 _, [%0];" ::"r"(b) : "memory"); }
#define MBAR_WAIT(SEM)                                                                                                         \
  asm volatile("{\n.reg .pred p;\n.reg .u32 it;\nmov.u32 it, 0;\nW:\nmbarrier.try_wait.parity" SEM ".shared::cta.b64 p, [%0], %1;\n" \
               "@p bra.uni D;\nadd.u32 it, it, 1;\nsetp.lt.u32 p, it, 0x400000;\n@p bra.uni W;\ntrap;\nD:\n}" ::"r"(b), "r"(ph) : "memory")
__device__ __forceinline__ void mbar_wait(uint32_t b, int ph) { MBAR_WAIT(""); }
__device__ __forceinline__ void tma2d(uint32_t dst, const CUtensorMap* m, int c0, int c1, uint32_t bar) {
  asm volatile("cp.async.bulk.tensor.2d.shared::cluster.global.mbarrier::complete_tx::bytes [%0], [%1, {%3, %4}], [%2];" ::"r"(dst), "l"(m), "r"(bar), "r"(c0), "r"(c1) : "memory");
}
__device__ __forceinline__ uint64_t pol_ef() { uint64_t p; asm("createpolicy.fractional.L2::evict_first.b64 %0, 1.0;" : "=l"(p)); return p; }
__device__ __forceinline__ void tma3d_ef(uint32_t dst, const CUtensorMap* m, int c1, int c2, uint32_t bar) {
  asm volatile("cp.async.bulk.tensor.3d.shared::cluster.global.mbarrier::complete_tx::bytes.L2::cache_hint [%0], [%1, {%3, %4, %5}], [%2], %6;" ::"r"(dst), "l"(m), "r"(bar), "r"(0), "r"(c1), "r"(c2), "l"(pol_ef()) : "memory");
}
__device__ __forceinline__ void tma4d_ef(uint32_t dst, const CUtensorMap* m, int c2, int c3, uint32_t bar) {
  asm volatile("cp.async.bulk.tensor.4d.shared::cluster.global.mbarrier::complete_tx::bytes.L2::cache_hint [%0], [%1, {%3, %3, %4, %5}], [%2], %6;" ::"r"(dst), "l"(m), "r"(bar), "r"(0), "r"(c2), "r"(c3), "l"(pol_ef()) : "memory");
}
__device__ __forceinline__ void bulk_ld(uint32_t dst, const void* src, int bytes, uint32_t bar) {
  asm volatile("cp.async.bulk.shared::cluster.global.mbarrier::complete_tx::bytes [%0], [%1], %2, [%3];" ::"r"(dst), "l"(src), "r"(bytes), "r"(bar) : "memory");
}
__device__ __forceinline__ void bulk_st(void* dst, uint32_t src, int bytes) {
  asm volatile("cp.async.bulk.global.shared::cta.bulk_group [%0], [%1], %2;" ::"l"(dst), "r"(src), "r"(bytes) : "memory");
}
__device__ __forceinline__ void tma_st2d(const CUtensorMap* m, uint32_t src, int c0, int c1) {
  asm volatile("cp.async.bulk.tensor.2d.global.shared::cta.bulk_group [%0, {%2, %3}], [%1];" ::"l"(m), "r"(src), "r"(c0), "r"(c1) : "memory");
}
__device__ __forceinline__ void bulk_commit_wait_read() {
  asm volatile("cp.async.bulk.commit_group;" ::: "memory");
  asm volatile("cp.async.bulk.wait_group.read 0;" ::: "memory");
}
__device__ __forceinline__ void bulk_commit_wait() {
  asm volatile("cp.async.bulk.commit_group;" ::: "memory");
  asm volatile("cp.async.bulk.wait_group 0;" ::: "memory");
}
__device__ __forceinline__ void prefetch_l2(const void* p, int bytes) {
  asm volatile("cp.async.bulk.prefetch.L2.global [%0], %1;" ::"l"(p), "r"(bytes) : "memory");
}
__device__ __forceinline__ void wg_fence() { asm volatile("wgmma.fence.sync.aligned;" ::: "memory"); }
__device__ __forceinline__ void wg_commit() { asm volatile("wgmma.commit_group.sync.aligned;" ::: "memory"); }
template <int N> __device__ __forceinline__ void wg_wait() { asm volatile("wgmma.wait_group.sync.aligned %0;" ::"n"(N) : "memory"); }
template <int N> __device__ __forceinline__ void reg_fence(float (&d)[N]) {
#pragma unroll
  for (int i = 0; i < N; i++) asm volatile("" : "+f"(d[i])::"memory");
}
__device__ __forceinline__ void fence_async_smem() { asm volatile("fence.proxy.async.shared::cta;" ::: "memory"); }
__device__ __forceinline__ void fence_async_glb() { asm volatile("fence.proxy.async.global;" ::: "memory"); }
__device__ __forceinline__ uint32_t ld_rlx(const void* p) { uint32_t v; asm volatile("ld.relaxed.gpu.global.b32 %0, [%1];" : "=r"(v) : "l"(p) : "memory"); return v; }
__device__ __forceinline__ uint2 ld_rlx2(const void* p) { uint2 v; asm volatile("ld.relaxed.gpu.global.v2.b32 {%0,%1}, [%2];" : "=r"(v.x), "=r"(v.y) : "l"(p) : "memory"); return v; }
__device__ __forceinline__ uint4 ld_rlx4(const void* p) { uint4 v; asm volatile("ld.relaxed.gpu.global.v4.b32 {%0,%1,%2,%3}, [%4];" : "=r"(v.x), "=r"(v.y), "=r"(v.z), "=r"(v.w) : "l"(p) : "memory"); return v; }
__device__ __forceinline__ uint32_t ld_nc(const void* p) { uint32_t v; asm volatile("ld.global.nc.L1::no_allocate.b32 %0, [%1];" : "=r"(v) : "l"(p) : "memory"); return v; }
__device__ __forceinline__ uint32_t lds(uint32_t a) { uint32_t v; asm volatile("ld.shared.b32 %0, [%1];" : "=r"(v) : "r"(a) : "memory"); return v; }
__device__ __forceinline__ uint2 lds2(uint32_t a) { uint2 v; asm volatile("ld.shared.v2.b32 {%0,%1}, [%2];" : "=r"(v.x), "=r"(v.y) : "r"(a) : "memory"); return v; }
__device__ __forceinline__ uint4 lds4(uint32_t a) { uint4 v; asm volatile("ld.shared.v4.b32 {%0,%1,%2,%3}, [%4];" : "=r"(v.x), "=r"(v.y), "=r"(v.z), "=r"(v.w) : "r"(a) : "memory"); return v; }
__device__ __forceinline__ float lds_bf(uint32_t a) { uint32_t v; asm volatile("ld.shared.u16 %0, [%1];" : "=r"(v) : "r"(a) : "memory"); return __uint_as_float(v << 16); }
__device__ __forceinline__ void sts(uint32_t a, uint32_t v) { asm volatile("st.shared.b32 [%0], %1;" ::"r"(a), "r"(v) : "memory"); }
__device__ __forceinline__ void sts2(uint32_t a, uint32_t v0, uint32_t v1) { asm volatile("st.shared.v2.b32 [%0], {%1,%2};" ::"r"(a), "r"(v0), "r"(v1) : "memory"); }
__device__ __forceinline__ void sts4(uint32_t a, uint32_t v0, uint32_t v1, uint32_t v2, uint32_t v3) { asm volatile("st.shared.v4.b32 [%0], {%1,%2,%3,%4};" ::"r"(a), "r"(v0), "r"(v1), "r"(v2), "r"(v3) : "memory"); }
__device__ __forceinline__ void bar_sync(int id, int n) { asm volatile("bar.sync %0, %1;" ::"r"(id), "r"(n) : "memory"); }
__device__ __forceinline__ void bar_arrive(int id, int n) { asm volatile("bar.arrive %0, %1;" ::"r"(id), "r"(n) : "memory"); }
__device__ __forceinline__ void red_add(unsigned* p, unsigned v) { asm volatile("red.relaxed.gpu.global.add.u32 [%0], %1;" ::"l"(p), "r"(v) : "memory"); }
__device__ __forceinline__ bool any(bool p) { return __any_sync(0xffffffffu, p); }
constexpr int SPIN_MAX = 1 << 20;
__device__ __forceinline__ void wait_cnt(const unsigned* p, unsigned target) {
  int it = 0;
  while (any((int)(ld_rlx(p) - target) < 0) && ++it < SPIN_MAX) {}
}
__device__ __forceinline__ uint32_t pack_bf16(float lo, float hi) { uint32_t r; asm("cvt.rn.bf16x2.f32 %0, %1, %2;" : "=r"(r) : "f"(hi), "f"(lo)); return r; }
__device__ __forceinline__ float bf_lo(uint32_t v) { return __uint_as_float(v << 16); }
__device__ __forceinline__ float bf_hi(uint32_t v) { return __uint_as_float(v & 0xffff0000u); }
__device__ __forceinline__ uint32_t hadd2(uint32_t a, uint32_t b) { uint32_t r; asm("add.rn.bf16x2 %0, %1, %2;" : "=r"(r) : "r"(a), "r"(b)); return r; }
__device__ __forceinline__ uint32_t hmul2(uint32_t a, uint32_t b) { uint32_t r; asm("mul.rn.bf16x2 %0, %1, %2;" : "=r"(r) : "r"(a), "r"(b)); return r; }
__device__ __forceinline__ uint32_t hfma2(uint32_t a, uint32_t b, uint32_t c) { uint32_t r; asm("fma.rn.bf16x2 %0, %1, %2, %3;" : "=r"(r) : "r"(a), "r"(b), "r"(c)); return r; }
__device__ __forceinline__ float rbf(float x) { uint32_t r; asm("cvt.rn.bf16x2.f32 %0, %1, %2;" : "=r"(r) : "f"(x), "f"(0.0f)); return __uint_as_float(r); }
__device__ __forceinline__ void stmatrix4(uint32_t a, uint32_t r0, uint32_t r1, uint32_t r2, uint32_t r3) {
  asm volatile("stmatrix.sync.aligned.m8n8.x4.shared.b16 [%0], {%1,%2,%3,%4};" ::"r"(a), "r"(r0), "r"(r1), "r"(r2), "r"(r3) : "memory");
}
__device__ __forceinline__ void stmatrix2(uint32_t a, uint32_t r0, uint32_t r1) {
  asm volatile("stmatrix.sync.aligned.m8n8.x2.shared.b16 [%0], {%1,%2};" ::"r"(a), "r"(r0), "r"(r1) : "memory");
}
__device__ __forceinline__ void stmatrix4t(uint32_t a, uint32_t r0, uint32_t r1, uint32_t r2, uint32_t r3) {
  asm volatile("stmatrix.sync.aligned.m8n8.x4.trans.shared.b16 [%0], {%1,%2,%3,%4};" ::"r"(a), "r"(r0), "r"(r1), "r"(r2), "r"(r3) : "memory");
}
__device__ __forceinline__ uint32_t movm(uint32_t a) { uint32_t r; asm("movmatrix.sync.aligned.m8n8.trans.b16 %0, %1;" : "=r"(r) : "r"(a)); return r; }
template <bool ACC> __device__ __forceinline__ void mma16(float* d, uint32_t a0, uint32_t a1, uint32_t a2, uint32_t a3, uint32_t b0, uint32_t b1) {
  if (ACC) asm("mma.sync.aligned.m16n8k16.row.col.f32.bf16.bf16.f32 {%0,%1,%2,%3}, {%4,%5,%6,%7}, {%8,%9}, {%0,%1,%2,%3};"
               : "+f"(d[0]), "+f"(d[1]), "+f"(d[2]), "+f"(d[3]) : "r"(a0), "r"(a1), "r"(a2), "r"(a3), "r"(b0), "r"(b1));
  else asm("mma.sync.aligned.m16n8k16.row.col.f32.bf16.bf16.f32 {%0,%1,%2,%3}, {%4,%5,%6,%7}, {%8,%9}, {%10,%10,%10,%10};"
           : "=f"(d[0]), "=f"(d[1]), "=f"(d[2]), "=f"(d[3]) : "r"(a0), "r"(a1), "r"(a2), "r"(a3), "r"(b0), "r"(b1), "f"(0.f));
}
__device__ __forceinline__ uint32_t pin(uint32_t v) { uint32_t r; asm volatile("shfl.sync.bfly.b32 %0, %1, 0, 31, 0xffffffff;" : "=r"(r) : "r"(v)); return r; }
__device__ __forceinline__ uint32_t set_tag(uint32_t w, uint32_t tag) { uint32_t r; asm("lop3.b32 %0, %1, 0xfffffffe, %2, 0xea;" : "=r"(r) : "r"(w), "r"(tag)); return r; }
__device__ __forceinline__ uint32_t diff2(uint32_t a, uint32_t b, uint32_t tag) { uint32_t r; asm("lop3.b32 %0, %1, %2, %3, 0x7e;" : "=r"(r) : "r"(a), "r"(b), "r"(tag)); return r; }
__device__ __forceinline__ float2 cmul(float2 a, float2 b) { return make_float2(a.x * b.x - a.y * b.y, a.x * b.y + a.y * b.x); }

template<int TB> __device__ __forceinline__ void wgmma_ss_160_0(float (&d)[80], uint32_t al, uint32_t ah, uint32_t bl, uint32_t bh) {
  asm volatile("{\n.reg .b64 da, db;\nmov.b64 da, {%80, %81};\nmov.b64 db, {%82, %83};\n"
    "wgmma.mma_async.sync.aligned.m64n160k16.f32.bf16.bf16 {%0,%1,%2,%3,%4,%5,%6,%7,%8,%9,%10,%11,%12,%13,%14,%15,%16,%17,%18,%19,%20,%21,%22,%23,%24,%25,%26,%27,%28,%29,%30,%31,%32,%33,%34,%35,%36,%37,%38,%39,%40,%41,%42,%43,%44,%45,%46,%47,%48,%49,%50,%51,%52,%53,%54,%55,%56,%57,%58,%59,%60,%61,%62,%63,%64,%65,%66,%67,%68,%69,%70,%71,%72,%73,%74,%75,%76,%77,%78,%79}, da, db, 1, 1, 1, 1, %84;\n}\n"
    : "+f"(d[0]),"+f"(d[1]),"+f"(d[2]),"+f"(d[3]),"+f"(d[4]),"+f"(d[5]),"+f"(d[6]),"+f"(d[7]),"+f"(d[8]),"+f"(d[9]),"+f"(d[10]),"+f"(d[11]),"+f"(d[12]),"+f"(d[13]),"+f"(d[14]),"+f"(d[15]),"+f"(d[16]),"+f"(d[17]),"+f"(d[18]),"+f"(d[19]),"+f"(d[20]),"+f"(d[21]),"+f"(d[22]),"+f"(d[23]),"+f"(d[24]),"+f"(d[25]),"+f"(d[26]),"+f"(d[27]),"+f"(d[28]),"+f"(d[29]),"+f"(d[30]),"+f"(d[31]),"+f"(d[32]),"+f"(d[33]),"+f"(d[34]),"+f"(d[35]),"+f"(d[36]),"+f"(d[37]),"+f"(d[38]),"+f"(d[39]),"+f"(d[40]),"+f"(d[41]),"+f"(d[42]),"+f"(d[43]),"+f"(d[44]),"+f"(d[45]),"+f"(d[46]),"+f"(d[47]),"+f"(d[48]),"+f"(d[49]),"+f"(d[50]),"+f"(d[51]),"+f"(d[52]),"+f"(d[53]),"+f"(d[54]),"+f"(d[55]),"+f"(d[56]),"+f"(d[57]),"+f"(d[58]),"+f"(d[59]),"+f"(d[60]),"+f"(d[61]),"+f"(d[62]),"+f"(d[63]),"+f"(d[64]),"+f"(d[65]),"+f"(d[66]),"+f"(d[67]),"+f"(d[68]),"+f"(d[69]),"+f"(d[70]),"+f"(d[71]),"+f"(d[72]),"+f"(d[73]),"+f"(d[74]),"+f"(d[75]),"+f"(d[76]),"+f"(d[77]),"+f"(d[78]),"+f"(d[79])
    : "r"(al), "r"(ah), "r"(bl), "r"(bh), "n"(TB));
}
template<int TB> __device__ __forceinline__ void wgmma_ss_144_0(float (&d)[80], uint32_t al, uint32_t ah, uint32_t bl, uint32_t bh) {
  asm volatile("{\n.reg .b64 da, db;\nmov.b64 da, {%72, %73};\nmov.b64 db, {%74, %75};\n"
    "wgmma.mma_async.sync.aligned.m64n144k16.f32.bf16.bf16 {%0,%1,%2,%3,%4,%5,%6,%7,%8,%9,%10,%11,%12,%13,%14,%15,%16,%17,%18,%19,%20,%21,%22,%23,%24,%25,%26,%27,%28,%29,%30,%31,%32,%33,%34,%35,%36,%37,%38,%39,%40,%41,%42,%43,%44,%45,%46,%47,%48,%49,%50,%51,%52,%53,%54,%55,%56,%57,%58,%59,%60,%61,%62,%63,%64,%65,%66,%67,%68,%69,%70,%71}, da, db, 1, 1, 1, 1, %76;\n}\n"
    : "+f"(d[0]),"+f"(d[1]),"+f"(d[2]),"+f"(d[3]),"+f"(d[4]),"+f"(d[5]),"+f"(d[6]),"+f"(d[7]),"+f"(d[8]),"+f"(d[9]),"+f"(d[10]),"+f"(d[11]),"+f"(d[12]),"+f"(d[13]),"+f"(d[14]),"+f"(d[15]),"+f"(d[16]),"+f"(d[17]),"+f"(d[18]),"+f"(d[19]),"+f"(d[20]),"+f"(d[21]),"+f"(d[22]),"+f"(d[23]),"+f"(d[24]),"+f"(d[25]),"+f"(d[26]),"+f"(d[27]),"+f"(d[28]),"+f"(d[29]),"+f"(d[30]),"+f"(d[31]),"+f"(d[32]),"+f"(d[33]),"+f"(d[34]),"+f"(d[35]),"+f"(d[36]),"+f"(d[37]),"+f"(d[38]),"+f"(d[39]),"+f"(d[40]),"+f"(d[41]),"+f"(d[42]),"+f"(d[43]),"+f"(d[44]),"+f"(d[45]),"+f"(d[46]),"+f"(d[47]),"+f"(d[48]),"+f"(d[49]),"+f"(d[50]),"+f"(d[51]),"+f"(d[52]),"+f"(d[53]),"+f"(d[54]),"+f"(d[55]),"+f"(d[56]),"+f"(d[57]),"+f"(d[58]),"+f"(d[59]),"+f"(d[60]),"+f"(d[61]),"+f"(d[62]),"+f"(d[63]),"+f"(d[64]),"+f"(d[65]),"+f"(d[66]),"+f"(d[67]),"+f"(d[68]),"+f"(d[69]),"+f"(d[70]),"+f"(d[71])
    : "r"(al), "r"(ah), "r"(bl), "r"(bh), "n"(TB));
}
template<int TB> __device__ __forceinline__ void wgmma_ss_96_0(float (&d)[80], uint32_t al, uint32_t ah, uint32_t bl, uint32_t bh) {
  asm volatile("{\n.reg .b64 da, db;\nmov.b64 da, {%48, %49};\nmov.b64 db, {%50, %51};\n"
    "wgmma.mma_async.sync.aligned.m64n96k16.f32.bf16.bf16 {%0,%1,%2,%3,%4,%5,%6,%7,%8,%9,%10,%11,%12,%13,%14,%15,%16,%17,%18,%19,%20,%21,%22,%23,%24,%25,%26,%27,%28,%29,%30,%31,%32,%33,%34,%35,%36,%37,%38,%39,%40,%41,%42,%43,%44,%45,%46,%47}, da, db, 1, 1, 1, 1, %52;\n}\n"
    : "+f"(d[0]),"+f"(d[1]),"+f"(d[2]),"+f"(d[3]),"+f"(d[4]),"+f"(d[5]),"+f"(d[6]),"+f"(d[7]),"+f"(d[8]),"+f"(d[9]),"+f"(d[10]),"+f"(d[11]),"+f"(d[12]),"+f"(d[13]),"+f"(d[14]),"+f"(d[15]),"+f"(d[16]),"+f"(d[17]),"+f"(d[18]),"+f"(d[19]),"+f"(d[20]),"+f"(d[21]),"+f"(d[22]),"+f"(d[23]),"+f"(d[24]),"+f"(d[25]),"+f"(d[26]),"+f"(d[27]),"+f"(d[28]),"+f"(d[29]),"+f"(d[30]),"+f"(d[31]),"+f"(d[32]),"+f"(d[33]),"+f"(d[34]),"+f"(d[35]),"+f"(d[36]),"+f"(d[37]),"+f"(d[38]),"+f"(d[39]),"+f"(d[40]),"+f"(d[41]),"+f"(d[42]),"+f"(d[43]),"+f"(d[44]),"+f"(d[45]),"+f"(d[46]),"+f"(d[47])
    : "r"(al), "r"(ah), "r"(bl), "r"(bh), "n"(TB));
}
template<int TB> __device__ __forceinline__ void wgmma_ss_48_48(float (&d)[80], uint32_t al, uint32_t ah, uint32_t bl, uint32_t bh) {
  asm volatile("{\n.reg .b64 da, db;\nmov.b64 da, {%24, %25};\nmov.b64 db, {%26, %27};\n"
    "wgmma.mma_async.sync.aligned.m64n48k16.f32.bf16.bf16 {%0,%1,%2,%3,%4,%5,%6,%7,%8,%9,%10,%11,%12,%13,%14,%15,%16,%17,%18,%19,%20,%21,%22,%23}, da, db, 1, 1, 1, 1, %28;\n}\n"
    : "+f"(d[48]),"+f"(d[49]),"+f"(d[50]),"+f"(d[51]),"+f"(d[52]),"+f"(d[53]),"+f"(d[54]),"+f"(d[55]),"+f"(d[56]),"+f"(d[57]),"+f"(d[58]),"+f"(d[59]),"+f"(d[60]),"+f"(d[61]),"+f"(d[62]),"+f"(d[63]),"+f"(d[64]),"+f"(d[65]),"+f"(d[66]),"+f"(d[67]),"+f"(d[68]),"+f"(d[69]),"+f"(d[70]),"+f"(d[71])
    : "r"(al), "r"(ah), "r"(bl), "r"(bh), "n"(TB));
}
__device__ __forceinline__ void wgmma_rs_72(float (&d)[36], uint32_t a0, uint32_t a1, uint32_t a2, uint32_t a3, uint32_t bl, uint32_t bh, int sd) {
  asm volatile("{\n.reg .pred p;\n.reg .b64 db;\nsetp.ne.b32 p, %42, 0;\nmov.b64 db, {%40, %41};\n"
    "wgmma.mma_async.sync.aligned.m64n72k16.f32.bf16.bf16 {%0,%1,%2,%3,%4,%5,%6,%7,%8,%9,%10,%11,%12,%13,%14,%15,%16,%17,%18,%19,%20,%21,%22,%23,%24,%25,%26,%27,%28,%29,%30,%31,%32,%33,%34,%35}, {%36,%37,%38,%39}, db, p, 1, 1, 1;\n}\n"
    : "+f"(d[0]),"+f"(d[1]),"+f"(d[2]),"+f"(d[3]),"+f"(d[4]),"+f"(d[5]),"+f"(d[6]),"+f"(d[7]),"+f"(d[8]),"+f"(d[9]),"+f"(d[10]),"+f"(d[11]),"+f"(d[12]),"+f"(d[13]),"+f"(d[14]),"+f"(d[15]),"+f"(d[16]),"+f"(d[17]),"+f"(d[18]),"+f"(d[19]),"+f"(d[20]),"+f"(d[21]),"+f"(d[22]),"+f"(d[23]),"+f"(d[24]),"+f"(d[25]),"+f"(d[26]),"+f"(d[27]),"+f"(d[28]),"+f"(d[29]),"+f"(d[30]),"+f"(d[31]),"+f"(d[32]),"+f"(d[33]),"+f"(d[34]),"+f"(d[35])
    : "r"(a0), "r"(a1), "r"(a2), "r"(a3), "r"(bl), "r"(bh), "r"(sd));
}
__device__ __forceinline__ void wgmma_rs_48(float (&d)[24], uint32_t a0, uint32_t a1, uint32_t a2, uint32_t a3, uint32_t bl, uint32_t bh, int sd) {
  asm volatile("{\n.reg .pred p;\n.reg .b64 db;\nsetp.ne.b32 p, %30, 0;\nmov.b64 db, {%28, %29};\n"
    "wgmma.mma_async.sync.aligned.m64n48k16.f32.bf16.bf16 {%0,%1,%2,%3,%4,%5,%6,%7,%8,%9,%10,%11,%12,%13,%14,%15,%16,%17,%18,%19,%20,%21,%22,%23}, {%24,%25,%26,%27}, db, p, 1, 1, 1;\n}\n"
    : "+f"(d[0]),"+f"(d[1]),"+f"(d[2]),"+f"(d[3]),"+f"(d[4]),"+f"(d[5]),"+f"(d[6]),"+f"(d[7]),"+f"(d[8]),"+f"(d[9]),"+f"(d[10]),"+f"(d[11]),"+f"(d[12]),"+f"(d[13]),"+f"(d[14]),"+f"(d[15]),"+f"(d[16]),"+f"(d[17]),"+f"(d[18]),"+f"(d[19]),"+f"(d[20]),"+f"(d[21]),"+f"(d[22]),"+f"(d[23])
    : "r"(a0), "r"(a1), "r"(a2), "r"(a3), "r"(bl), "r"(bh), "r"(sd));
}
template<int N,int OFF,int TB> __device__ __forceinline__ void wgmma_ss(float (&d)[80], uint32_t al, uint32_t ah, uint32_t bl, uint32_t bh) {
  if constexpr (N==160) wgmma_ss_160_0<TB>(d, al, ah, bl, bh);
  else if constexpr (N==144) wgmma_ss_144_0<TB>(d, al, ah, bl, bh);
  else if constexpr (N==96) wgmma_ss_96_0<TB>(d, al, ah, bl, bh);
  else if constexpr (N==48) wgmma_ss_48_48<TB>(d, al, ah, bl, bh);
}

__device__ __forceinline__ void dft3(float2& a, float2& b, float2& c) {
  const float s = 0.86602540378443864676f;
  float2 t = make_float2(b.x + c.x, b.y + c.y), d = make_float2(b.x - c.x, b.y - c.y);
  float2 m = make_float2(fmaf(-0.5f, t.x, a.x), fmaf(-0.5f, t.y, a.y));
  a = make_float2(a.x + t.x, a.y + t.y);
  b = make_float2(fmaf(s, d.y, m.x), fmaf(-s, d.x, m.y));
  c = make_float2(fmaf(-s, d.y, m.x), fmaf(s, d.x, m.y));
}
__device__ __forceinline__ void dft9(float2 (&x)[9]) {
  const float2 w1 = make_float2(0.76604444311897803520f, -0.64278760968653932632f);
  const float2 w2 = make_float2(0.17364817766693034885f, -0.98480775301220805937f);
  const float2 w4 = make_float2(-0.93969262078590838405f, -0.34202014332566873304f);
  dft3(x[0], x[3], x[6]); dft3(x[1], x[4], x[7]); dft3(x[2], x[5], x[8]);
  x[4] = cmul(x[4], w1); x[7] = cmul(x[7], w2); x[5] = cmul(x[5], w2); x[8] = cmul(x[8], w4);
  dft3(x[0], x[1], x[2]); dft3(x[3], x[4], x[5]); dft3(x[6], x[7], x[8]);
  float2 t;
  t = x[1]; x[1] = x[3]; x[3] = t;
  t = x[2]; x[2] = x[6]; x[6] = t;
  t = x[5]; x[5] = x[7]; x[7] = t;
}

__device__ __forceinline__ int mod_pos(int u, int i) { return 16 * u + (u < 72 ? 2 * (i & 7) + (i >> 3) : i); }
__device__ __forceinline__ void mod_fma(float (&acc)[8], float sc, const uint4& w) {
  acc[0] = fmaf(sc, bf_lo(w.x), acc[0]); acc[1] = fmaf(sc, bf_hi(w.x), acc[1]);
  acc[2] = fmaf(sc, bf_lo(w.y), acc[2]); acc[3] = fmaf(sc, bf_hi(w.y), acc[3]);
  acc[4] = fmaf(sc, bf_lo(w.z), acc[4]); acc[5] = fmaf(sc, bf_hi(w.z), acc[5]);
  acc[6] = fmaf(sc, bf_lo(w.w), acc[6]); acc[7] = fmaf(sc, bf_hi(w.w), acc[7]);
}
__device__ __forceinline__ void mod_finish(const Params& p, float (&acc)[8], int u, int t128, uint32_t red, uint32_t tag) {
#pragma unroll
  for (int n = 4, o = 2; n; n >>= 1, o <<= 1) {
    const bool up = t128 & o;
#pragma unroll
    for (int e = 0; e < n; e++) acc[e] = (up ? acc[e + n] : acc[e]) + __shfl_xor_sync(0xffffffffu, up ? acc[e] : acc[e + n], o);
  }
  acc[0] += __shfl_xor_sync(0xffffffffu, acc[0], 16);
  const int col = 8 * (t128 & 1) + 2 * (t128 & 2) + ((t128 >> 1) & 2) + ((t128 >> 3) & 1);
  if (!(t128 & 16)) sts(red + (col * 4 + (t128 >> 5)) * 4, __float_as_uint(acc[0]));
  bar_sync(4, 128);
  if (t128 < 16) {
    const uint4 v = lds4(red + t128 * 16);
    float m = rbf((__uint_as_float(v.x) + __uint_as_float(v.y)) + (__uint_as_float(v.z) + __uint_as_float(v.w)));
    const int kind = u / 36;
    if (kind == 0) m *= 16.0f;
    if (kind == 1 || kind == 4) m = rbf(1.0f + m);
    p.s->mod[mod_pos(u, t128)] = __float_as_uint(m) | tag;
  }
}

__device__ __forceinline__ void ln_stats2(const float (&a)[18], const float (&b)[18], float sc, float& oa, float& ra, float& ob, float& rb) {
  float v[4] = {0.f, 0.f, 0.f, 0.f}, w[4] = {0.f, 0.f, 0.f, 0.f};
#pragma unroll
  for (int i = 0; i < 18; i += 2) {
    v[0] += a[i]; v[1] = fmaf(a[i], a[i], v[1]); v[2] += b[i]; v[3] = fmaf(b[i], b[i], v[3]);
    w[0] += a[i + 1]; w[1] = fmaf(a[i + 1], a[i + 1], w[1]); w[2] += b[i + 1]; w[3] = fmaf(b[i + 1], b[i + 1], w[3]);
  }
#pragma unroll
  for (int e = 0; e < 4; e++) v[e] += w[e];
#pragma unroll
  for (int o = 16; o; o >>= 1) {
#pragma unroll
    for (int e = 0; e < 4; e++) v[e] += __shfl_xor_sync(0xffffffffu, v[e], o);
  }
  const float ma = v[0] * (1.0f / D_), mb = v[2] * (1.0f / D_);
  ra = sc * rsqrtf(fmaxf(fmaf(-ma, ma, v[1] * (1.0f / D_)), 0.f) + 1e-5f);
  rb = sc * rsqrtf(fmaxf(fmaf(-mb, mb, v[3] * (1.0f / D_)), 0.f) + 1e-5f);
  oa = -ma * ra; ob = -mb * rb;
}

__device__ __forceinline__ float tmat(int c, int q, int j) {
  const int ph = q == 1 ? 1024 * j : (q >> 1) * (c + 128 * j) + 512 * (q & 1);
  return __cosf((float)(((ph + 1024) & 2047) - 1024) * (6.283185307179586f / 2048.0f));
}
__device__ __forceinline__ uint32_t line_off(int k1, int kap, int pi, int f) {
  int kd = 64 * k1 + 9 * kap;
  if (kap == 0 && k1 > 4) kd -= 288;
  if (kd >= D_) kd -= D_;
  return pi * 2400 + ((min(kd, D_ - kd) ^ f) << 3);
}

constexpr int JSK = 5;
struct Ring { uint32_t st, ph; };
template <bool G2, class T> __device__ __forceinline__ void ring_next(T& st, T& ph) {
  if (++st == NST) st = 0;
  ph ^= ((G2 ? 0xDu : 0x1u) >> st) & 1;
}
__device__ __forceinline__ void arrive_if(uint32_t a, uint32_t p) {
  asm volatile("{\n.reg .pred p;\nsetp.ne.u32 p, %1, 0;\n@p mbarrier.arrive.shared::cta.b64 _, [%0];\n}" ::"r"(a), "r"(p) : "memory");
}
template <int NA> __device__ __forceinline__ void reg_fence_n(float (&d)[80]) {
#pragma unroll
  for (int i = 0; i < NA; i++) asm volatile("" : "+f"(d[i])::"memory");
}
template <int MODE>
__device__ __forceinline__ void gemm_main(float (&acc)[80], uint32_t da0, uint32_t da1, uint32_t db0, uint32_t db1, int wg, Ring& rg, uint32_t full0) {
  static_assert(JSK == NST - 1, "the held slot is the first one that is not refilled by GEMM1");
  constexpr int NKB = MODE == 3 ? 36 : 32;
  constexpr uint32_t HA = 0x40000040u, HB = MODE == 3 ? 0x40000040u : 0x80000020u;
  constexpr uint32_t KA = 2048 >> 4, KB = MODE == 3 ? (32 >> 4) : (1024 >> 4);
  constexpr int NA = MODE ? 72 : 80;
  const uint32_t t = threadIdx.x & 127;
  const uint32_t eb = full0 + 8 * NST;
  uint32_t pb = 0, rel = t == 0, prel = 0;
  int n = NKB - JSK;
#pragma unroll 1
  for (int pass = 0;; pass++) {
#pragma unroll 1
    do {
      const uint32_t so = rg.st * (STAGE >> 4);
      mbar_wait(full0 + 8 * rg.st, rg.ph);
      reg_fence_n<NA>(acc);
      wg_fence();
#pragma unroll
      for (int k = 0; k < 4; k++) {
        if (MODE == 0) wgmma_ss<160, 0, 1>(acc, da0 + so + k * KA, HA, db0 + so + k * KB, HB);
        else if (MODE == 3) wgmma_ss<144, 0, 0>(acc, da0 + so + k * KA, HA, db0 + so + k * KB, HB);
        else {
          wgmma_ss<96, 0, 1>(acc, da0 + so + k * KA, HA, db0 + so + k * KB, HB);
          wgmma_ss<48, 48, 1>(acc, da1 + so + k * KA, HA, db1 + so + k * KB, HB);
        }
      }
      wg_commit();
      wg_wait<1>();
      reg_fence_n<NA>(acc);
      arrive_if(pb, prel);
      pb = eb + 8 * rg.st; prel = rel;
      ring_next<MODE == 3>(rg.st, rg.ph);
    } while (--n);
    if (pass == 2 - wg) break;
    n = 1;
    if (pass == 0) {
      if (MODE != 3) prel = rel & wg;
      else rel = 0;
      n = JSK - 1 + wg;
      if (!wg) continue;
      wg_wait<0>();
      arrive_if(pb, prel);
      prel = 0;
    }
    bar_sync(1, 256);
  }
  wg_wait<0>();
  reg_fence_n<NA>(acc);
  if (MODE != 3) arrive_if(pb, prel & ~wg);
}

__device__ __forceinline__ float gelu_arg(float h) { return h * fmaf(8.0f * 0.044715f * 0.7978845608028654f, h * h, 2.0f * 0.7978845608028654f); }

__device__ __forceinline__ int kb2_order(int i) { const int wv = i / 6; return 6 * (i - 6 * wv) + ((0x431250 >> (4 * wv)) & 7); }

__device__ __forceinline__ void wait_flags(const unsigned* base, int n, int idx, unsigned target, uint64_t& ready) {
  if ((ready >> idx) & 1) return;
  const int l = threadIdx.x & 31;
  int it = 0;
  while (true) {
    unsigned a = ld_rlx(base + l), b = l + 32 < n ? ld_rlx(base + l + 32) : target;
    ready = (uint64_t)__ballot_sync(0xffffffffu, (int)(a - target) >= 0) | ((uint64_t)__ballot_sync(0xffffffffu, (int)(b - target) >= 0) << 32);
    if (((ready >> idx) & 1) || ++it > SPIN_MAX) break;
  }
  fence_async_glb();
}

enum { B_FULL = 0, B_EMPTY = 6, B_FLT = 12, B_Z1, B_Z2, B_GO, B_S4, B_S5, B_WM, B_NUM, B_W0 = B_NUM };

__global__ void __launch_bounds__(NTHR, 1)
fused_kernel(const Params p, const __grid_constant__ Maps maps) {
  extern __shared__ uint8_t smem_raw[];
  __shared__ uint64_t bars[B_NUM + 1];
  __shared__ __align__(16) float redbuf[128 + D_];

  const uint32_t sbase = (smem_u32(smem_raw) + 1023) & ~1023u;
  const uint32_t full0 = smem_u32(bars), empty0 = full0 + 8 * B_EMPTY, red = smem_u32(redbuf);
  const int tid = threadIdx.x, cta = blockIdx.x, t128 = tid & 127;
  const int wp = __shfl_sync(0xffffffffu, tid >> 5, 0), wg = wp >> 2;
  const int l = tid & 31, g = l >> 2, t = l & 3;
  Scratch* const sc = p.s;
  const bool rows = cta < 128;
  const int R = cta - 12;

  uint32_t xr[18];
  uint32_t cv[9];
  const unsigned ep = ld_rlx(&sc->cnt[C_EP]) + 1;
  if (tid == 0) TS(0);
  if (wg == 2) {
#pragma unroll
    for (int i = 0; i < 9; i++) asm volatile("ld.global.nc.u16 %0, [%1];" : "=r"(cv[i]) : "l"(p.c + (t128 >> 1) + 64 * i) : "memory");
    if (wp == 9 && l < 9 && rows) {
      const int h = 9 * cta + l;
      prefetch_l2(reinterpret_cast<const uint8_t*>(p.wmod) + (size_t)(h >> 1) * (12 * D_) + (h & 1) * (2 * D_), 2 * D_);
    }
    if (t128 < 16) {
#pragma unroll 1
      for (int u = cta < 72 ? cta : 72 + cta; u < 216; u += u < 72 ? 72 : NCTA) sc->mod[mod_pos(u, t128)] = 0;
    }
    if (tid == 256 && cta < 72) {
      mbar_init(full0 + 8 * B_W0, 1);
      fence_async_smem();
      mbar_expect(full0 + 8 * B_W0, 18432);
#pragma unroll 1
      for (int i = 0; i < 3; i++) tma2d(sbase + O_P2 + i * 6144, &maps.wm, 16 * cta, 192 * i, full0 + 8 * B_W0);
    }
    if (tid == 352) {
#pragma unroll 1
      for (int i = 0; i < B_NUM; i++) mbar_init(full0 + 8 * i, i == B_FLT ? 4 : i == B_WM ? 3 : i >= B_EMPTY && i < B_FLT ? 2 : 1);
      fence_async_smem();
    }
    if (wp == 10 && l < 12) asm volatile("prefetch.tensormap [%0];" ::"l"(&maps.w1a + l) : "memory");
    __syncwarp();
  }
  CK(0);
  auto load_x = [&]() {
    const uint32_t* xs = reinterpret_cast<const uint32_t*>(p.x) + (size_t)(cta + 256 * wp) * 288 + l;
#pragma unroll
    for (int i = 0; i < 9; i++) { xr[i] = ld_nc(xs + 32 * i); xr[9 + i] = ld_nc(xs + 128 * 288 + 32 * i); }
  };
  if (rows && wg < 2) load_x();
  if (tid == 64 && cta == NCTA - 1) prefetch_l2(p.tab, sizeof(T_TAB));
  __syncwarp();
  const uint32_t tag16 = (ep & 0x7fffu) | 0x8000u, tag1 = ep & 1u;

  if (wg == 2) {
    float sil[9];
#pragma unroll
    for (int i = 0; i < 9; i++) sil[i] = rbf(__fdividef(bf_lo(cv[i]), 1.0f + __expf(-bf_lo(cv[i]))));
    if (cta < 72) {
      float acc[8] = {0.f, 0.f, 0.f, 0.f, 0.f, 0.f, 0.f, 0.f};
      bar_sync(4, 128);
      mbar_wait(full0 + 8 * B_W0, 0);
      if (t128 == 0) TS(10);
#pragma unroll
      for (int i = 0; i < 9; i++) mod_fma(acc, sil[i], lds4(sbase + O_P2 + t128 * 16 + i * 2048));
      mod_finish(p, acc, cta, t128, red, tag16);
      if (t128 == 0) TS(25);
    }
#pragma unroll
    for (int i = 0; i < 9; i++) sts(red + 512 + ((t128 >> 1) + 64 * i) * 4, __float_as_uint(sil[i]));
    CK(1);
  }
  const int pi = R / 15, col0 = 20 * (R - 15 * pi);
  const int xu = DF_ * pi + col0, xv = DF_ * (pi ? 16 - pi : 8) + col0;
  auto load_filter = [&](int a) {
    const int x = (a & 1) ? xv : xu;
    const bool wide = (x & 15) > 12;
    mbar_expect(full0 + 8 * B_FLT, wide ? 12288 : 8192);
    tma2d(sbase + O_RAW + a * 12288, &maps.wf[a & 2], x & ~15, 0, full0 + 8 * B_FLT);
    if (wide) tma2d(sbase + O_RAW + a * 12288 + 8192, &maps.wf[(a & 2) + 1], (x & ~15) + 32, 0, full0 + 8 * B_FLT);
  };
  const int kap = 8 * ((wp & 3) ^ (wg & 1)) + g;
  uint4 af[4];
  if (rows) {
    uint32_t tb[4];
#pragma unroll
    for (int i = 0; i < 4; i++) tb[i] = pack_bf16(tmat(cta, 8 * (i >> 1) + g, 2 * t + 8 * (i & 1)), tmat(cta, 8 * (i >> 1) + g, 2 * t + 8 * (i & 1) + 1));
    uint32_t sb1[3], lo[9];
#pragma unroll
    for (int i = 0; i < 4; i++) tb[i] = pin(tb[i]);
#pragma unroll
    for (int i = 0; i < 3; i++) {
      const int d = 48 * wp + 16 * i + (l & 15);
      sb1[i] = pin(sbase + O_B1 + (l >> 4) * 9216 + (d % 9) * 1024 + (d & 63) * 16);
    }
    const uint32_t snt = pin(sbase + O_NRM + ((l & 7) + 8 * (l >> 4)) * 1168 + (48 * wp + (l & 8)) * 2);
    if (wg < 2) {
#pragma unroll
      for (int k1 = 0; k1 < 9; k1++) lo[k1] = pin(sbase + O_Z1 + line_off(k1, kap, 4 * wg + t, cta & 3));
#pragma unroll
      for (int kk = 0; kk < 4; kk++) af[kk] = __ldg(p.tab + TB_F + kk * 128 + (t128 ^ (wg << 5)));
      float a[18], b[18];
#pragma unroll
      for (int i = 0; i < 9; i++) { a[2 * i] = bf_lo(xr[i]); a[2 * i + 1] = bf_hi(xr[i]); b[2 * i] = bf_lo(xr[9 + i]); b[2 * i + 1] = bf_hi(xr[9 + i]); }
      float oa, ra, ob, rb;
      ln_stats2(a, b, 1.0f, oa, ra, ob, rb);
      CK(1);
      const uint32_t sn = sbase + O_NRM + wp * 2336 + l * 4;
#pragma unroll
      for (int i = 0; i < 9; i++) {
        sts(sn + i * 128, pack_bf16(fmaf(a[2 * i], ra, oa), fmaf(a[2 * i + 1], ra, oa)));
        sts(sn + 1168 + i * 128, pack_bf16(fmaf(b[2 * i], rb, ob), fmaf(b[2 * i + 1], rb, ob)));
      }
      CK(2);
      bar_arrive(10, NTHR);
      bar_sync(1, 256);
      if (tid == 0) TS(2);
    } else {
      bar_sync(10, NTHR);
      CK(2);
    }
    float rs[3][8];
#pragma unroll
    for (int i = 0; i < 3; i++) {
      uint32_t a0, a1, a2, a3;
      asm volatile("ldmatrix.sync.aligned.m8n8.x4.trans.shared.b16 {%0,%1,%2,%3}, [%4];" : "=r"(a0), "=r"(a1), "=r"(a2), "=r"(a3)
                   : "r"(snt + 32 * i) : "memory");
      mma16<false>(&rs[i][0], a0, a1, a2, a3, tb[0], tb[1]);
      mma16<false>(&rs[i][4], a0, a1, a2, a3, tb[2], tb[3]);
    }
    CK(3);
    {
      uint2 ms[3], mc[3];
      const uint32_t* mp = sc->mod + 48 * wp + 2 * g;
      int it = 0;
#pragma unroll 1
      while (true) {
        uint32_t bad = 0;
#pragma unroll
        for (int i = 0; i < 3; i++) { ms[i] = ld_rlx2(mp + 16 * i); mc[i] = ld_rlx2(mp + D_ + 16 * i); }
#pragma unroll
        for (int i = 0; i < 3; i++) {
          ms[i].x ^= tag16; ms[i].y ^= tag16; mc[i].x ^= tag16; mc[i].y ^= tag16;
          bad |= ms[i].x | ms[i].y | mc[i].x | mc[i].y;
        }
        if (!any(bad & 0xffffu) || ++it > SPIN_MAX) break;
      }
      CK(4);
      if (tid == 0) TS(3);
#pragma unroll
      for (int i = 0; i < 3; i++) {
        const float c0 = __uint_as_float(mc[i].x), c1 = __uint_as_float(mc[i].y);
        const float s0 = t ? 0.f : __uint_as_float(ms[i].x), s1 = t ? 0.f : __uint_as_float(ms[i].y);
        stmatrix4(sb1[i], pack_bf16(fmaf(rs[i][0], c0, s0), rs[i][1] * c0), pack_bf16(fmaf(rs[i][2], c1, s1), rs[i][3] * c1),
                  pack_bf16(rs[i][4] * c0, rs[i][5] * c0), pack_bf16(rs[i][6] * c1, rs[i][7] * c1));
      }
    }
    fence_async_smem();
    CK(5);
    if (wg == 2) {
      bar_arrive(5, NTHR);
      if (l == 0 && R >= 0) load_filter(wp - 8);
      __syncwarp();
    } else {
      bar_sync(5, NTHR);
      CK(6);
      float acc[36];
      const uint32_t db = (((sbase + O_B1 + wg * 9216) & 0x3FFFF) >> 4) | ((128 >> 4) << 16);
      wg_fence();
#pragma unroll
      for (int kk = 0; kk < 4; kk++) wgmma_rs_72(acc, af[kk].x, af[kk].y, af[kk].z, af[kk].w, db + kk * 16, 1024 >> 4, kk);
      wg_commit();
      wg_wait<0>();
      reg_fence(acc);
      CK(7);
      float2 za[9], zb[9];
#pragma unroll
      for (int i = 0; i < 9; i++) { za[i] = make_float2(acc[4 * i], acc[4 * i + 2]); zb[i] = make_float2(acc[4 * i + 1], acc[4 * i + 3]); }
      dft9(za); dft9(zb);
      if (kap == 0) {
#pragma unroll
        for (int k = 1; k < 5; k++) {
          float2 a = za[k], b = za[9 - k];
          za[k] = make_float2(a.x + b.x, a.y - b.y); za[9 - k] = make_float2(a.y + b.y, b.x - a.x);
          a = zb[k]; b = zb[9 - k];
          zb[k] = make_float2(a.x + b.x, a.y - b.y); zb[9 - k] = make_float2(a.y + b.y, b.x - a.x);
        }
        sts2(lo[0] + 288 * 8, set_tag(pack_bf16(za[0].y, 0.f), tag1), pack_bf16(zb[0].y, 0.f));
        za[0].y = 0.f; zb[0].y = 0.f;
      }
      __syncwarp();
#pragma unroll
      for (int k1 = 0; k1 < 9; k1++) sts2(lo[k1], set_tag(pack_bf16(za[k1].x, za[k1].y), tag1), pack_bf16(zb[k1].x, zb[k1].y));
      fence_async_smem();
      CK(8);
      bar_arrive(2 + wg, 160);
    }
  } else {
    __syncthreads();
  }

  if ((wp >> 1) == 4) {
    if (rows) bar_sync(wp - 6, 160);
    else { int it = 0; while (any((ld_rlx(sc->mod + 36 * l) ^ tag16) & 0xffffu) && ++it < SPIN_MAX) {} }
    if (l == 0) {
      const int slot = 4 * (cta & 7) + ((cta >> 4) & 3) + 32 * (2 * (cta >> 6) + ((cta >> 3) & 1));
      if (rows) {
        tma_st2d(&maps.z1, sbase + O_Z1 + (wp - 8) * 9600, 40 * slot, 60 * (wp - 8));
        HW();
        red_add(&sc->cnt[C_Z1 + 32 * (wp - 8)], 1);
        if (wp == 8) TS(4);
      } else { load_filter(wp - 8); load_filter(wp - 6); }
    }
    __syncwarp();
  }
  auto load_wm = [&](int u) {
    if (wp > 8 && l == 0) {
      mbar_expect(full0 + 8 * B_WM, 6144);
      tma2d(sbase + O_NRM + (wp - 9) * 6144, &maps.wm, 16 * u, 192 * (wp - 9), full0 + 8 * B_WM);
    }
    __syncwarp();
  };
  if (R >= 0) {
    const int ln0 = wg < 2 ? 2 * wp : 8 + wp;
    const int nl = min(wg < 2 ? 2 : 1, DF_ - col0 - ln0);
    uint4 cf[2][4], G[4];
#pragma unroll
    for (int i = 0; i < 4; i++) {
      cf[0][i] = __ldg(p.tab + TB_P2 + i * 32 + l);
      cf[1][i] = __ldg(p.tab + TB_P2 + (pi ? i : 4 + i) * 32 + l);
      G[i] = __ldg(p.tab + TB_P2 + (8 + i) * 32 + l);
    }
    const uint32_t* zin = sc->z1 + (size_t)R * 5120;
    if (wp == 10) {
      wait_cnt(&sc->cnt[C_Z1 + 32 * (pi >> 2)], 128 * ep);
      if (l == 0) {
        TS(12);
        mbar_expect(full0 + 8 * B_Z1, 20480);
        bulk_ld(sbase + O_P2, zin, 20480, full0 + 8 * B_Z1);
      }
      __syncwarp();
    }
    mbar_wait(full0 + 8 * B_FLT, 0);
    CK(9);
    float wn[16], wc[16];
#pragma unroll 1
    for (int ln = nl - 1; ln >= 0; ln--) {
      const int col = col0 + ln0 + ln, k2 = (57 * col) & 63;
      const bool cj = k2 > 32 || (k2 == 32 && col != 288);
      const float nr = ((col & 31) == 0 && col != 0 && col != 288 ? 0.5f : 1.0f) / ((float)S_ * D_), ni = cj ? -nr : nr;
#pragma unroll
      for (int i = 0; i < 16; i++) wn[i] = wc[i];
#pragma unroll
      for (int cl = 0; cl < 2; cl++) {
        const int v = cl ^ (cj && pi), e = ((v ? xv : xu) & 15) + ln0 + ln, sh = e < 32 ? 6 : 5;
        const uint32_t base = sbase + O_RAW + v * 12288 + (e < 32 ? 2 * e : 8192 - 64 + 2 * e), msk = e < 32 ? 0x30 : 0x10;
        const int dm = v ? (cj || pi ? -1 : 0) : 0;
#pragma unroll
        for (int tt = 0; tt < 4; tt++) {
          const int kc = g + 64 * (tt >> 1) + 16 * t + 8 * (tt & 1);
          uint32_t a = base + ((((cj ? -kc : kc) + dm) & 127) << sh);
          a ^= (a >> 3) & msk;
          wc[4 * tt + 2 * cl] = lds_bf(a) * nr; wc[4 * tt + 2 * cl + 1] = lds_bf(a + 24576) * ni;
        }
      }
    }
    const float al = pi ? 1.0f : 0.0f;
    CK(10);
    uint32_t off = pin(l * 160 + ((ln0 ^ (g & 3)) << 3));
    mbar_wait(full0 + 8 * B_Z1, 0);
    CK(11);
    if (tid == 0) TS(8);
    if (wg == 2) load_wm(72 + cta);
#pragma unroll 1
    for (int ln = 0; ln < nl; ln++, off ^= 8) {
      uint2 v[4];
#pragma unroll
      for (int i = 0; i < 4; i++) v[i] = lds2(sbase + O_P2 + off + i * 5120);
      if (__builtin_expect(any((diff2(v[0].x, v[1].x, tag1) | diff2(v[2].x, v[3].x, tag1)) & 1), 0)) {
        FAILCNT(0);
        int it = 0;
        do {
#pragma unroll
          for (int i = 0; i < 4; i++) v[i] = ld_rlx2(reinterpret_cast<const uint8_t*>(zin) + off + i * 5120);
        } while (any((diff2(v[0].x, v[1].x, tag1) | diff2(v[2].x, v[3].x, tag1)) & 1) && ++it < SPIN_MAX);
      }
      float d[4][4];
      uint32_t A[8];
#pragma unroll
      for (int h = 0; h < 2; h++) {
        mma16<false>(d[2 * h], cf[0][0].x, cf[0][0].y, cf[0][0].z, cf[0][0].w, v[h].x, v[2 + h].x);
        mma16<false>(d[2 * h + 1], cf[1][0].x, cf[1][0].y, cf[1][0].z, cf[1][0].w, v[h].y, v[2 + h].y);
      }
#pragma unroll
      for (int h = 0; h < 2; h++)
#pragma unroll
        for (int L = 0; L < 2; L++) {
          const uint4 tw = cf[L][2 + h];
          const float* z = d[2 * h + L];
          const float2 z0 = cmul(make_float2(z[0], z[2]), make_float2(__uint_as_float(tw.x), __uint_as_float(tw.y)));
          const float2 z1 = cmul(make_float2(z[1], z[3]), make_float2(__uint_as_float(tw.z), __uint_as_float(tw.w)));
          A[4 * h + L] = pack_bf16(z0.x, z0.y); A[4 * h + 2 + L] = pack_bf16(z1.x, z1.y);
        }
#pragma unroll
      for (int tt = 0; tt < 4; tt++) {
        mma16<false>(d[tt], A[0], A[1], A[2], A[3], G[tt].x, G[tt].y);
        mma16<true>(d[tt], A[4], A[5], A[6], A[7], G[tt].z, G[tt].w);
      }
#pragma unroll
      for (int tt = 0; tt < 4; tt++) {
        const float ar = d[tt][0], aj = d[tt][1], br = d[tt][2], bj = d[tt][3];
        const float2 y1 = cmul(make_float2(fmaf(-al, bj, ar), fmaf(al, br, aj)), make_float2(wc[4 * tt], wc[4 * tt + 1]));
        const float2 y2 = cmul(make_float2(fmaf(al, ar, bj), fmaf(al, aj, -br)), make_float2(wc[4 * tt + 2], wc[4 * tt + 3]));
        A[2 * tt] = pack_bf16(fmaf(al, y2.x, y1.x), fmaf(-al, y2.y, -y1.y));
        A[2 * tt + 1] = pack_bf16(fmaf(al, y1.y, -y2.y), fmaf(al, y1.x, -y2.x));
      }
#pragma unroll
      for (int i = 0; i < 16; i++) wc[i] = wn[i];
#pragma unroll
      for (int tt = 0; tt < 4; tt++) {
        mma16<false>(d[tt], A[0], A[1], A[2], A[3], G[tt].x, G[tt].y);
        mma16<true>(d[tt], A[4], A[5], A[6], A[7], G[tt].z, G[tt].w);
      }
#pragma unroll
      for (int h = 0; h < 2; h++)
#pragma unroll
        for (int L = 0; L < 2; L++) {
          const uint4 tw = cf[L][2 + h];
          const float2 z0 = cmul(make_float2(d[2 * h][2 * L], d[2 * h][2 * L + 1]), make_float2(__uint_as_float(tw.x), __uint_as_float(tw.y)));
          const float2 z1 = cmul(make_float2(d[2 * h + 1][2 * L], d[2 * h + 1][2 * L + 1]), make_float2(__uint_as_float(tw.z), __uint_as_float(tw.w)));
          A[4 * h + 2 * L] = movm(pack_bf16(z0.x, z1.x)); A[4 * h + 2 * L + 1] = movm(pack_bf16(z0.y, z1.y));
        }
#pragma unroll
      for (int h = 0; h < 2; h++) {
        mma16<false>(d[0], cf[0][1].x, cf[0][1].y, cf[0][1].z, cf[0][1].w, A[4 * h], A[4 * h + 1]);
        mma16<false>(d[1], cf[1][1].x, cf[1][1].y, cf[1][1].z, cf[1][1].w, A[4 * h + 2], A[4 * h + 3]);
#pragma unroll
        for (int e = 0; e < 2; e++)
          sts2(sbase + O_P2 + off + (2 * h + e) * 5120, set_tag(pack_bf16(d[0][e], d[0][2 + e]), tag1), pack_bf16(d[1][e], d[1][2 + e]));
      }
      CK(12 + ln);
    }
    fence_async_smem();
    if (wp) bar_arrive(6, NTHR);
    else {
      bar_sync(6, NTHR);
      if (l == 0) {
        tma_st2d(&maps.z2, sbase + O_P2, 40 * R, 0);
        HW();
        red_add(&sc->cnt[C_Z2], 1);
        TS(9);
      }
      __syncwarp();
    }
  }
  if (wg == 2) {
#pragma unroll 1
    for (int u = 72 + cta, k = 0; u < 216; u += NCTA, k ^= 1) {
      if (R < 0) { fence_async_smem(); bar_sync(4, 128); load_wm(u); }
      mbar_wait(full0 + 8 * B_WM, k);
      float acc[8] = {0.f, 0.f, 0.f, 0.f, 0.f, 0.f, 0.f, 0.f};
#pragma unroll 1
      for (int i = 0; i < 9; i++) mod_fma(acc, __uint_as_float(lds(red + 512 + ((t128 >> 1) + 64 * i) * 4)), lds4(sbase + O_NRM + t128 * 16 + i * 2048));
      mod_finish(p, acc, u, t128, red + 256 - 256 * k, tag16);
    }
    fence_async_smem();
    CK(13);
  }

  const int grp = cta / 11, m1 = cta - 11 * grp;
  const bool helper = (m1 & 3) == 3;
  const int f1 = 384 * grp + (helper ? 192 : 128) * (m1 >> 2);
  const int d1 = 160 * (m1 & 3), flip = m1 >= 7;
  const int a1bytes = helper ? 24576 : 16384;
  auto load_a1 = [&](int st, int kb) {
    mbar_expect(full0 + 8 * st, STAGE);
    tma4d_ef(sbase + st * STAGE, helper ? &maps.w1b : &maps.w1a, 4 * kb, f1 >> 6, full0 + 8 * st);
  };

  if (rows) {
#pragma unroll
    for (int kk = 0; kk < 4; kk++) af[kk] = __ldg(p.tab + TB_E + kk * 128 + t128);
    uint32_t tb[4], sy[6];
#pragma unroll
    for (int i = 0; i < 4; i++) tb[i] = pack_bf16(tmat(cta, 2 * t + 8 * (i & 1), 8 * (i >> 1) + g), tmat(cta, 2 * t + 8 * (i & 1) + 1, 8 * (i >> 1) + g));
#pragma unroll
    for (int i = 0; i < 6; i++) {
      const int rr = 16 * (wp & 3) + g + 8 * (i & 1);
      sy[i] = pin(sbase + O_Y + (t * 584 + 64 * ((3 * wg + (i >> 1) + 63 - rr) % 9) + rr) * 4);
    }
#pragma unroll
    for (int i = 0; i < 4; i++) tb[i] = pin(tb[i]);
    const int slot = 4 * (cta >> 4) + ((cta >> 1) & 3) + 32 * (2 * ((cta >> 3) & 1) + (cta & 1));
    const uint32_t* zin = sc->z2 + (size_t)slot * 4800;
    if (wg == 2) {
      {
        uint4 v[4];
        const int i3 = min(t128 + 384, 431);
        int it = 0;
        while (true) {
          uint32_t bad = 0;
#pragma unroll
          for (int k = 0; k < 4; k++) v[k] = ld_rlx4(sc->mod + 2 * D_ + 4 * (k < 3 ? t128 + 128 * k : i3));
#pragma unroll
          for (int k = 0; k < 4; k++) {
            v[k].x ^= tag16; v[k].y ^= tag16; v[k].z ^= tag16; v[k].w ^= tag16;
            bad |= v[k].x | v[k].y | v[k].z | v[k].w;
          }
          if (!any(bad & 0xffffu) || ++it > SPIN_MAX) break;
        }
#pragma unroll
        for (int k = 0; k < 4; k++) sts4(sbase + O_MOD + 16 * (k < 3 ? t128 + 128 * k : i3), v[k].x, v[k].y, v[k].z, v[k].w);
      }
      CK(14);
      mbar_wait(full0 + 8 * B_Z2, 0);
      if (l == 0) {
        load_a1(wp - 8, wp - 8);
        if (wp > 8 && wp - 8 < NG1) prefetch_l2(reinterpret_cast<const uint8_t*>(p.w1) + (size_t)(128 * (cta >> 3) + 16 * (wp - 8) + 2 * (cta & 7)) * (2 * F_), 4 * F_);
      }
      __syncwarp();
    } else {
      uint32_t lo[9];
#pragma unroll
      for (int k1 = 0; k1 < 9; k1++) lo[k1] = pin(sbase + O_IN + line_off(k1, kap, 4 * wg + t, (cta >> 4) & 3));
      const uint32_t lx = pin(lo[0] + (kap ? 0 : 288 * 8));
      const uint32_t sb3 = pin(sbase + O_B3 + wg * 1024 + (l >> 4) * 2048 + (2 * (kap & 24) + (l & 15)) * 16);
      CK(14);
      if (wp == 0) {
        wait_cnt(&sc->cnt[C_Z2], 120 * ep);
        if (l == 0) {
          TS(14);
          mbar_expect(full0 + 8 * B_Z2, 19200);
          bulk_ld(sbase + O_IN, zin, 19200, full0 + 8 * B_Z2);
        }
        __syncwarp();
      }
      mbar_wait(full0 + 8 * B_Z2, 0);
      CK(15);
      if (tid == 0) TS(11);
      uint2 v[10];
      uint32_t bad = 0;
#pragma unroll
      for (int k1 = 0; k1 < 10; k1++) v[k1] = lds2(k1 < 9 ? lo[k1] : lx);
#pragma unroll
      for (int k1 = 0; k1 < 10; k1 += 2) bad |= diff2(v[k1].x, v[k1 + 1].x, tag1);
      if (__builtin_expect(any(bad & 1), 0)) {
        FAILCNT(1);
        int it = 0;
        do {
          bad = 0;
#pragma unroll
          for (int k1 = 0; k1 < 10; k1++) v[k1] = ld_rlx2(reinterpret_cast<const uint8_t*>(zin) + ((k1 < 9 ? lo[k1] : lx) - (sbase + O_IN)));
#pragma unroll
          for (int k1 = 0; k1 < 10; k1 += 2) bad |= diff2(v[k1].x, v[k1 + 1].x, tag1);
        } while (any(bad & 1) && ++it < SPIN_MAX);
      }
      float2 za[9], zb[9];
#pragma unroll
      for (int i = 0; i < 9; i++) { za[i] = make_float2(bf_lo(v[i].x), bf_hi(v[i].x)); zb[i] = make_float2(bf_lo(v[i].y), bf_hi(v[i].y)); }
      if (kap == 0) {
#pragma unroll
        for (int k = 1; k < 5; k++) {
          float2 a = za[k], b = za[9 - k];
          za[k] = make_float2(a.x - b.y, a.y + b.x); za[9 - k] = make_float2(a.x + b.y, b.x - a.y);
          a = zb[k]; b = zb[9 - k];
          zb[k] = make_float2(a.x - b.y, a.y + b.x); zb[9 - k] = make_float2(a.x + b.y, b.x - a.y);
        }
        za[0].y = bf_lo(v[9].x); zb[0].y = bf_lo(v[9].y);
      }
      __syncwarp();
      dft9(za); dft9(zb);
#pragma unroll
      for (int n = 0; n < 8; n += 2) {
        const int i0 = (9 - n) % 9, i1 = 8 - n;
        stmatrix4(sb3 + n * 2048, pack_bf16(za[i0].x, zb[i0].x), pack_bf16(za[i0].y, zb[i0].y), pack_bf16(za[i1].x, zb[i1].x), pack_bf16(za[i1].y, zb[i1].y));
      }
      stmatrix2(sb3 + 8 * 2048, pack_bf16(za[1].x, zb[1].x), pack_bf16(za[1].y, zb[1].y));
      fence_async_smem();
    }
    CK(16);
    __syncthreads();
    CK(17);
    float acc[24];
    const uint32_t db = (((sbase + O_B3 + wg * 6144) & 0x3FFFF) >> 4) | ((128 >> 4) << 16);
    wg_fence();
#pragma unroll
    for (int kk = 0; kk < 4; kk++) wgmma_rs_48(acc, af[kk].x, af[kk].y, af[kk].z, af[kk].w, db + kk * 16, 1024 >> 4, kk);
    wg_commit();
    uint32_t ga[9];
    uint2 sh[9], sw[9];
    if (wg < 2) {
#pragma unroll
      for (int i = 0; i < 9; i++) {
        const uint2 v = lds2(sbase + O_MOD + (64 * i + 2 * l) * 4);
        ga[i] = __byte_perm(v.x, v.y, 0x7632);
        sh[i] = lds2(sbase + O_MOD + (D_ + 64 * i + 2 * l) * 4);
        sw[i] = lds2(sbase + O_MOD + (2 * D_ + 64 * i + 2 * l) * 4);
      }
    }
    wg_wait<0>();
    reg_fence(acc);
    CK(18);
#pragma unroll
    for (int i = 0; i < 3; i++) {
      const float* a = &acc[8 * i];
      const uint32_t a0 = pack_bf16(a[0], a[1]), a1 = pack_bf16(a[2], a[3]), a2 = pack_bf16(a[4], a[5]), a3 = pack_bf16(a[6], a[7]);
#pragma unroll
      for (int jh = 0; jh < 2; jh++) {
        float y[4];
        mma16<false>(y, a0, a1, a2, a3, tb[2 * jh], tb[2 * jh + 1]);
        sts(sy[2 * i] + jh * (4 * 584 * 4), pack_bf16(y[0], y[1]));
        sts(sy[2 * i + 1] + jh * (4 * 584 * 4), pack_bf16(y[2], y[3]));
      }
    }
    CK(19);
    if (wg == 2) bar_arrive(7, NTHR);
    else {
      bar_sync(7, NTHR);
      CK(20);
      float a[18], b[18];
#pragma unroll
      for (int i = 0; i < 9; i++) {
        const uint2 y = lds2(sbase + O_Y + (wp * 584 + 64 * i + 2 * l) * 4);
        xr[i] = hfma2(ga[i], __byte_perm(y.x, y.y, 0x5410), xr[i]);
        xr[9 + i] = hfma2(ga[i], __byte_perm(y.x, y.y, 0x7632), xr[9 + i]);
        a[2 * i] = bf_lo(xr[i]); a[2 * i + 1] = bf_hi(xr[i]); b[2 * i] = bf_lo(xr[9 + i]); b[2 * i + 1] = bf_hi(xr[9 + i]);
      }
      float oa, ra, ob, rb;
      ln_stats2(a, b, 1.0f, oa, ra, ob, rb);
      CK(21);
#pragma unroll
      for (int i = 0; i < 9; i++) {
        const float c0 = __uint_as_float(sw[i].x), c1 = __uint_as_float(sw[i].y), s0 = __uint_as_float(sh[i].x), s1 = __uint_as_float(sh[i].y);
        a[2 * i] = fmaf(fmaf(a[2 * i], ra, oa), c0, s0); a[2 * i + 1] = fmaf(fmaf(a[2 * i + 1], ra, oa), c1, s1);
        b[2 * i] = fmaf(fmaf(b[2 * i], rb, ob), c0, s0); b[2 * i + 1] = fmaf(fmaf(b[2 * i + 1], rb, ob), c1, s1);
      }
      ln_stats2(a, b, 0.5f, oa, ra, ob, rb);
      CK(22);
      const uint32_t sh3 = sbase + O_IN + (l >> 4) * 1024 + wp * 128 + ((((l >> 2) ^ wp) & 3) << 4) + (l & 3) * 4;
#pragma unroll
      for (int i = 0; i < 9; i++) {
        sts(sh3 + i * 2048, pack_bf16(fmaf(a[2 * i], ra, oa), fmaf(a[2 * i + 1], ra, oa)));
        sts(sh3 + i * 2048 + 64, pack_bf16(fmaf(b[2 * i], rb, ob), fmaf(b[2 * i + 1], rb, ob)));
      }
      fence_async_smem();
      bar_arrive(8, 288);
      CK(23);
      const uint32_t sx = sbase + O_B3 + wp * 2304 + l * 4;
#pragma unroll
      for (int i = 0; i < 9; i++) { sts(sx + i * 128, xr[i]); sts(sx + 1152 + i * 128, xr[9 + i]); }
      fence_async_smem();
      bar_arrive(9, 288);
    }
  } else __syncthreads();

  const bool g2 = cta < 130 && (cta >> 1) != 56;
  const int z2 = cta < 112 ? cta : cta - 2, r = z2 >> 6;
  const int s2 = 128 * ((z2 >> 2) & 15), d2 = 144 * (z2 & 3);
  constexpr int XST = (33 + 36 - JSK - 1) % NST;
  constexpr int ST0 = (32 - JSK - 1) % NST, ST1 = 31 % NST;

  if (wg == 2) {
    asm volatile("setmaxnreg.dec.sync.aligned.u32 40;");
    if (wp == 8) {
      int st = rows ? 4 : 0, ph = 1;
#pragma unroll 1
      for (int kb = st; kb < 32; kb++) {
        if (rows && kb < 6) mbar_wait(full0 + 8 * (B_S4 - 4 + kb), 0);
        mbar_wait(empty0 + 8 * st, ph);
        if (l == 0) {
          load_a1(st, kb);
          if (kb >= PF2K && kb < PF2K + PF2 && g2)
            prefetch_l2(reinterpret_cast<const uint8_t*>(p.w2) + (size_t)(36 * r + kb2_order(kb - PF2K)) * 262144 + (z2 & 63) * 4096, 4096);
        }
        __syncwarp();
        ring_next<false>(st, ph);
      }
      if (g2) {
        st++;
#pragma unroll 1
        for (int i = 0; i < 36; i++) {
          if (i == HOLDA) mbar_wait(full0 + 8 * B_GO, 0);
          mbar_wait(empty0 + 8 * st, ph);
          if (l == 0) {
            mbar_expect(full0 + 8 * st, 16384 + 18432);
            tma3d_ef(sbase + st * STAGE, &maps.w2, 64 * (36 * r + kb2_order(i)), s2 >> 6, full0 + 8 * st);
          }
          __syncwarp();
          ring_next<true>(st, ph);
        }
      }
    } else if (wp >= 10) {
      const int sw = wp - 10;
      if (rows) {
        bar_sync(9 - sw, 288);
        if (!sw) mbar_wait(full0, 0);
        if (l == 0) {
          if (sw) {
            tma_st2d(&maps.h3, sbase + O_IN, 256 * (cta & 3), 18 * (cta >> 2));
            bulk_commit_wait();
            TS(1);
            mbar_arrive(full0 + 8 * B_S4);
            asm volatile("fence.acq_rel.gpu;" ::: "memory");
            red_add(&sc->cnt[C_H3 + (cta >> 2)], 1);
            TS(13);
          } else {
#pragma unroll 1
            for (int j = 0; j < 16; j++) bulk_st(sc->x1 + (size_t)(cta + 128 * j) * 288, sbase + O_B3 + j * 1152, 1152);
            bulk_commit_wait();
            mbar_arrive(full0 + 8 * B_S5);
          }
        }
        __syncwarp();
      }
      if (sw && g2) {
        mbar_wait(full0 + 8 * 5, 0);
#pragma unroll 1
        for (int i = 0; i < 36; i++) { sc->part[z2 * 1152 + 32 * i + l] = make_uint4(tag1 ^ 1, 0, 0, 0); __nanosleep(100); }
        __syncwarp();
      }
      const uint32_t stg = sbase + (sw ? ST1 : ST0) * STAGE;
      const int kbA = (f1 >> 6) + (helper ? 2 : 1) * (sw ^ flip), kbB = helper ? (f1 >> 6) + 1 : kbA;
      const int dB = helper ? d1 + 32 * sw : d1 + 96;
      bar_sync(11 + sw, 160);
      if (l == 0) { TS(sw ? 31 : 30); bulk_st(sc->u + ((size_t)kbA * D_ + d1) * 128, stg, 96 * 128); }
      __syncwarp();
      bar_sync(13 + sw, 160);
      if (l == 0) {
        bulk_st(sc->u + ((size_t)kbB * D_ + dB) * 128, stg + 96 * 128, helper ? 32 * 128 : 64 * 128);
        if (helper) bulk_st(sc->u + ((size_t)kbB * D_ + d1 + 64 + 16 * sw) * 128, stg + 128 * 128, 16 * 128);
        bulk_commit_wait();
        mbar_arrive(empty0 + 8 * (sw ? ST1 : ST0));
        if (sw == 0) TS(26);
        asm volatile("fence.acq_rel.gpu;" ::: "memory");
        red_add(&sc->cnt[C_U + kbA], 2);
        if (helper) red_add(&sc->cnt[C_U + kbB], 1);
        TS(sw ? 23 : 17);
      }
      __syncwarp();
    } else {
      uint64_t ready = 0;
      int st = 0, ph = 1;
#pragma unroll 1
      for (int kb = 0; kb < 32; kb++) {
        if (rows && (kb >> 1) == 2) mbar_wait(full0 + 8 * (B_S4 - 4 + kb), 0);
        mbar_wait(empty0 + 8 * st, ph);
        wait_flags(sc->cnt + C_H3, 32, kb, 4 * ep, ready);
        if (l == 0) bulk_ld(sbase + st * STAGE + a1bytes, sc->h3 + ((size_t)(kb * 18 + (d1 >> 5)) << 12), STAGE - a1bytes, full0 + 8 * st);
        ring_next<false>(st, ph);
      }
      if (g2) {
        ready = 0;
        st++;
#pragma unroll 1
        for (int i = 0; i < 72; i++) {
          if (i == 36) ready = 0;
          const int kb = kb2_order(i < 36 ? i : i - 36), hf = r ^ (i >= 36);
          if (i <= 36) mbar_wait(empty0 + 8 * st, ph);
          wait_flags(sc->cnt + C_U + 36 * hf, 36, kb, 8 * ep, ready);
          if (i < 36) {
            if (l == 0) {
              bulk_ld(sbase + st * STAGE + 16384, sc->u + ((size_t)(36 * r + kb) * D_ + d2) * 128, 18432, full0 + 8 * st);
              if (i == GOAT) mbar_arrive(full0 + 8 * B_GO);
            }
            ring_next<true>(st, ph);
          } else if (ready == ~0ull) break;
        }
        if (l == 0) mbar_expect(full0 + 8 * XST, 18432);
        __syncwarp();
        if (l < 3) tma2d(sbase + XST * STAGE + 18432 + l * 6144, &maps.x1, d2 + 48 * l, s2 + 64 * (r ^ 1), full0 + 8 * XST);
        __syncwarp();
      }
    }
  } else {
    asm volatile("setmaxnreg.inc.sync.aligned.u32 232;");
    const int wgu = wg;
    const uint32_t sb4 = sbase >> 4, fullu = full0;
    const int w = wp & 3;
    Ring rg = {0, 0};
    float acc[80];
    constexpr uint32_t LA = (8192 >> 4) << 16, LB = (4096 >> 4) << 16;
    {
      const int fa = f1 + (helper ? 128 : 64) * (wg ^ flip) + 16 * w + g, fb = helper ? f1 + 64 + 16 * w + g : fa;
      const float a0 = 0.5f * __bfloat162float(p.b1[fa]), a1 = 0.5f * __bfloat162float(p.b1[fa + 8]);
      const float b0 = 0.5f * __bfloat162float(p.b1[fb]), b1 = 0.5f * __bfloat162float(p.b1[fb + 8]);
#pragma unroll
      for (int i = 0; i < 80; i++) acc[i] = i < 48 ? ((i & 2) ? a1 : a0) : ((i & 2) ? b1 : b0);
      reg_fence(acc);
    }
    if (!helper) gemm_main<0>(acc, sb4 + (wgu ^ flip) * 512 + LA, 0, sb4 + 1024 + LB, 0, wgu, rg, fullu);
    else {
      float ac2[80];
#pragma unroll
      for (int i = 0; i < 72; i++) asm volatile("mov.b32 %0, %1;" : "=f"(ac2[i]) : "f"(acc[i]));
      gemm_main<1>(ac2, sb4 + (wgu ^ flip) * 1024 + LA, sb4 + 512 + LA, sb4 + 1536 + LB, sb4 + 1536 + (wgu ? 256 + LB + (2 << 16) : 2 * LB), wgu, rg, fullu);
#pragma unroll
      for (int i = 0; i < 72; i++) asm volatile("mov.b32 %0, %1;" : "=f"(acc[i]) : "f"(ac2[i]));
    }
    if (t128 == 0) TS(wg ? 16 : 6);
    {
      const int mi = l >> 3, rr = l & 7;
      const uint32_t ad = sbase + (wg ? ST1 : ST0) * STAGE + (8 * (mi >> 1) + rr) * 128 + (((2 * w + (mi & 1)) ^ rr) << 4);
      float z[2][16];
#pragma unroll
      for (int j = -1; j <= 5; j++) {
        if (j >= 1) {
          const float* a = &acc[16 * (j - 1)];
          const float* tt = z[(j - 1) & 1];
#pragma unroll
          for (int h = 0; h < 16; h += 8)
            stmatrix4t(ad + (2 * (j - 1) + (h >> 3)) * 2048, pack_bf16(fmaf(a[h], tt[h], a[h]), fmaf(a[h + 1], tt[h + 1], a[h + 1])),
                       pack_bf16(fmaf(a[h + 2], tt[h + 2], a[h + 2]), fmaf(a[h + 3], tt[h + 3], a[h + 3])),
                       pack_bf16(fmaf(a[h + 4], tt[h + 4], a[h + 4]), fmaf(a[h + 5], tt[h + 5], a[h + 5])),
                       pack_bf16(fmaf(a[h + 6], tt[h + 6], a[h + 6]), fmaf(a[h + 7], tt[h + 7], a[h + 7])));
        }
        if (j >= 0 && j < 5) {
#pragma unroll
          for (int e = 0; e < 16; e++) asm("tanh.approx.f32 %0, %0;" : "+f"(z[j & 1][e]));
        }
        if (j < 4) {
#pragma unroll
          for (int e = 0; e < 16; e++) z[(j + 1) & 1][e] = gelu_arg(acc[16 * (j + 1) + e]);
        }
        if (j == 3 || j == 5) { fence_async_smem(); asm volatile("bar.arrive %0, 160;" ::"r"((j == 3 ? 11 : 13) + wgu) : "memory"); }
        if (j < 5) {
          if (j >= 0) reg_fence(z[j & 1]);
          if (j < 4) reg_fence(z[(j + 1) & 1]);
          if (__builtin_expect(sb4 == 0x7ffffff0u + j, 0)) __trap();
          reg_fence(acc);
        }
      }
      if (t128 == 0) TS(wg ? 29 : 28);
    }
    if (g2) {
      const int mb = wgu ^ r;
      uint32_t gb[18];
      {
        float a0 = 0.f, a1 = 0.f;
        if (wgu) {
          a0 = __bfloat162float(p.b2[s2 + 64 * mb + 16 * w + g]); a1 = __bfloat162float(p.b2[s2 + 64 * mb + 16 * w + 8 + g]);
          int it = 0;
          uint32_t bad;
          do {
            bad = 0;
#pragma unroll
            for (int i = 0; i < 18; i++) {
              const uint2 v = ld_rlx2(sc->mod + 5 * D_ + d2 + 8 * i + 2 * t);
              bad |= (v.x ^ tag16) | (v.y ^ tag16);
              gb[i] = __byte_perm(v.x, v.y, 0x7632);
            }
          } while (any(bad & 0xffffu) && ++it < SPIN_MAX);
        }
#pragma unroll
        for (int i = 0; i < 72; i++) acc[i] = (i & 2) ? a1 : a0;
      }
      rg.st++;
      gemm_main<3>(acc, sb4 + mb * 512 + LA, 0, sb4 + 1024 + (1 << 16), 0, wgu, rg, fullu);
      if (t128 == 0) TS(wg ? 20 : 19);
      const uint32_t sx = sbase + XST * STAGE;
      if (wgu == 0) {
        uint4* dst = sc->part + z2 * 1152 + t128;
#pragma unroll
        for (int j = 0; j < 9; j++) {
          const float* a = &acc[8 * j];
          dst[j * 128] = make_uint4(set_tag(pack_bf16(a[0], a[1]), tag1), pack_bf16(a[2], a[3]), pack_bf16(a[4], a[5]), pack_bf16(a[6], a[7]));
        }
        if (tid == 0) TS(21);
        const uint4* src = sc->part + (z2 ^ 64) * 1152 + t128;
        uint4 v[9];
        uint32_t bad;
        int it = 0;
        do {
#pragma unroll
          for (int j = 0; j < 9; j++) v[j] = ld_rlx4(src + j * 128);
          bad = v[8].x ^ tag1;
#pragma unroll
          for (int j = 0; j < 8; j += 2) bad |= diff2(v[j].x, v[j + 1].x, tag1);
        } while (any(bad & 1) && ++it < SPIN_MAX);
#pragma unroll
        for (int j = 0; j < 9; j++) sts4(sx + t128 * 16 + j * 2048, v[j].x, v[j].y, v[j].z, v[j].w);
        bar_arrive(2 + w, 64);
        if (w == 0) {
#pragma unroll 1
          for (int i = 0; i < 3; i++) {
            bar_sync(11 + i, 160);
            if (l == 0) tma_st2d(&maps.out, sx + 18432 + i * 6144, d2 + 48 * i, s2 + 64 * (r ^ 1));
            __syncwarp();
          }
          if (l == 0) { bulk_commit_wait_read(); TS(22); }
          __syncwarp();
        }
      } else {
        mbar_wait(fullu + 8 * XST, rg.ph);
        bar_sync(2 + w, 64);
        if (t128 == 0) TS(5);
        if (tid == 128 && cta == 0) sc->cnt[C_EP] = ep;
        const uint32_t xa = sx + 18432 + (16 * w + (l & 15)) * 96 + (l >> 4) * 16;
#pragma unroll
        for (int c = 0; c < 3; c++) {
          uint32_t pv[3][4], xv[3][4];
#pragma unroll
          for (int j = 0; j < 3; j++) {
            asm volatile("ld.shared.v4.b32 {%0,%1,%2,%3}, [%4];" : "=r"(pv[j][0]), "=r"(pv[j][1]), "=r"(pv[j][2]), "=r"(pv[j][3]) : "r"(sx + t128 * 16 + (3 * c + j) * 2048) : "memory");
            asm volatile("ldmatrix.sync.aligned.m8n8.x4.shared.b16 {%0,%1,%2,%3}, [%4];" : "=r"(xv[j][0]), "=r"(xv[j][1]), "=r"(xv[j][2]), "=r"(xv[j][3]) : "r"(xa + c * 6144 + j * 32) : "memory");
          }
#pragma unroll
          for (int j = 0; j < 3; j++) {
            const float* a = &acc[8 * (3 * c + j)];
            uint32_t o[4];
#pragma unroll
            for (int e = 0; e < 4; e++)
              o[e] = hadd2(xv[j][e], hmul2(gb[2 * (3 * c + j) + (e >> 1)], pack_bf16(a[2 * e] + bf_lo(pv[j][e]), a[2 * e + 1] + bf_hi(pv[j][e]))));
            stmatrix4(xa + c * 6144 + j * 32, o[0], o[1], o[2], o[3]);
          }
          fence_async_smem();
          asm volatile("bar.arrive %0, 160;" ::"r"(11 + c) : "memory");
        }
        if (t128 == 0) TS(7);
        __syncwarp();
      }
    }
  }
}

typedef CUresult (*EncodeFn)(CUtensorMap*, CUtensorMapDataType, cuuint32_t, void*, const cuuint64_t*, const cuuint64_t*, const cuuint32_t*,
                             const cuuint32_t*, CUtensorMapInterleave, CUtensorMapSwizzle, CUtensorMapL2promotion, CUtensorMapFloatOOBfill);

struct Dim { cuuint64_t n, stride; cuuint32_t box; };
template <int RANK>
void make_map(EncodeFn enc, CUtensorMap* m, bool words, int swz, const void* ptr, const Dim (&d)[RANK]) {
  cuuint64_t gd[RANK], gs[RANK];
  cuuint32_t bx[RANK], es[RANK];
  for (int i = 0; i < RANK; i++) { gd[i] = d[i].n; gs[i] = d[i].stride; bx[i] = d[i].box; es[i] = 1; }
  enc(m, words ? CU_TENSOR_MAP_DATA_TYPE_UINT32 : CU_TENSOR_MAP_DATA_TYPE_BFLOAT16, RANK, const_cast<void*>(ptr), gd, gs + 1, bx, es,
      CU_TENSOR_MAP_INTERLEAVE_NONE, static_cast<CUtensorMapSwizzle>(swz),
      swz == 3 ? CU_TENSOR_MAP_L2_PROMOTION_L2_256B : CU_TENSOR_MAP_L2_PROMOTION_NONE, CU_TENSOR_MAP_FLOAT_OOB_FILL_NONE);
}

}

extern "C" void kernel_launch(void* const* d_in, const int* in_sizes, int n_in, void* d_out, int out_size) {
  (void)in_sizes; (void)n_in; (void)out_size;
  static EncodeFn enc = nullptr;
  static void *sptr = nullptr, *tptr = nullptr;
  if (!enc) {
    void* f = nullptr; cudaDriverEntryPointQueryResult qr;
    cudaGetDriverEntryPoint("cuTensorMapEncodeTiled", &f, cudaEnableDefault, &qr);
    enc = reinterpret_cast<EncodeFn>(f);
    cudaFuncSetAttribute(fused_kernel, cudaFuncAttributeMaxDynamicSharedMemorySize, SMEM_BYTES);
    cudaGetSymbolAddress(&sptr, g_s);
    cudaGetSymbolAddress(&tptr, T_TAB);
  }
  Params p;
  p.x = (const __nv_bfloat16*)d_in[0]; p.wr = (const __nv_bfloat16*)d_in[1]; p.wi = (const __nv_bfloat16*)d_in[2];
  p.b1 = (const __nv_bfloat16*)d_in[5]; p.b2 = (const __nv_bfloat16*)d_in[7];
  p.c = (const __nv_bfloat16*)d_in[8]; p.wmod = (const __nv_bfloat16*)d_in[9];
  p.w1 = (const __nv_bfloat16*)d_in[4]; p.w2 = (const __nv_bfloat16*)d_in[6];
  p.s = static_cast<Scratch*>(sptr); p.tab = static_cast<const uint4*>(tptr);
  Maps maps;
  make_map<4>(enc, &maps.w1a, false, 3, p.w1, {{64, 0, 64}, {16, 128 * 2 * F_, 16}, {128, 2 * F_, 4}, {72, 128, 2}});
  make_map<4>(enc, &maps.w1b, false, 3, p.w1, {{64, 0, 64}, {16, 128 * 2 * F_, 16}, {128, 2 * F_, 4}, {72, 128, 3}});
  make_map<3>(enc, &maps.w2, false, 3, p.w2, {{64, 0, 64}, {F_, 2 * S_, 64}, {32, 128, 2}});
  make_map<2>(enc, &maps.x1, false, 0, p.s->x1, {{D_, 0, 48}, {S_, 2 * D_, 64}});
  make_map<2>(enc, &maps.out, false, 0, d_out, {{D_, 0, 48}, {S_, 2 * D_, 64}});
  make_map<2>(enc, &maps.z1, true, 0, p.s->z1, {{5120, 0, 40}, {120, 20480, 60}});
  make_map<2>(enc, &maps.z2, true, 0, p.s->z2, {{4800, 0, 40}, {128, 19200, 128}});
  for (int i = 0; i < 4; i++) make_map<2>(enc, &maps.wf[i], false, 2 - (i & 1), (i & 2) ? p.wi : p.wr, {{16 * DF_, 0, (i & 1) ? 16u : 32u}, {128, 32 * DF_, 128}});
  make_map<2>(enc, &maps.wm, false, 0, p.wmod, {{6 * D_, 0, 16}, {D_, 12 * D_, 192}});
  make_map<2>(enc, &maps.h3, true, 0, p.s->h3, {{1024, 0, 256}, {32 * 18, 4096, 18}});
  fused_kernel<<<NCTA, NTHR, SMEM_BYTES, cudaStreamPerThread>>>(p, maps);
}
```

```cpp
#include <cuda_runtime.h>
#include <cuda_bf16.h>
#include <cuda.h>
#include <stdint.h>

namespace {

constexpr int S_ = 2048, D_ = 576, DF_ = 289, F_ = 4608;
constexpr int NCTA = 132, NTHR = 384;
constexpr int STAGE = 36864, NST = 6;
constexpr int SMEM_BYTES = NST * STAGE + 1024;
constexpr int O_NRM = 0, O_B1 = 19456, O_Z1 = 38912, O_P2 = 59392;
constexpr int O_RAW = 4 * STAGE;
constexpr int O_IN = 4 * STAGE, O_Y = O_IN + 19456, O_B3 = O_IN + 38912, O_MOD = O_IN + 57344;

__device__ __align__(128) const uint32_t T_TAB[5632] = {
0x3f803f80,0xbf803f80,0x3f803f80,0xbf803f80,0x3f803f80,0xbf803f80,0x3f803f80,0xbf803f80,0x3f803f80,0xbf803f80,0x3f803f80,0xbf803f80,
0x3f803f80,0xbf803f80,0x3f803f80,0xbf803f80,0x3f7f3f80,0xbdc90000,0x3f223f35,0xbf46bf35,0x3f753f7b,0xbe95be48,0x3ef13f0e,0xbf62bf55,
0x3f623f6d,0xbef1bec4,0x3e953ec4,0xbf75bf6d,0x3f463f55,0xbf22bf0e,0x3dc93e48,0xbf7fbf7b,0x3f7b3f80,0xbe480000,0xbe480000,0xbf7bbf80,
0x3f553f6d,0xbf0ebec4,0xbf0ebec4,0xbf55bf6d,0x3f0e3f35,0xbf55bf35,0xbf55bf35,0xbf0ebf35,0x3e483ec4,0xbf7bbf6d,0xbf7bbf6d,0xbe48bec4,
0x3f753f80,0xbe950000,0xbf62bf35,0xbef1bf35,0x3f223f55,0xbf46bf0e,0xbf7fbf7b,0x3dc9be48,0x3dc93ec4,0xbf7fbf6d,0xbf46bf6d,0x3f223ec4,
0xbef1be48,0xbf62bf7b,0xbe95bf0e,0x3f753f55,0x3f6d3f80,0xbec40000,0xbf6dbf80,0x3ec40000,0x3ec43f35,0xbf6dbf35,0xbec4bf35,0x3f6d3f35,
0xbec40000,0xbf6dbf80,0x3ec40000,0x3f6d3f80,0xbf6dbf35,0xbec4bf35,0x3f6d3f35,0x3ec43f35,0x3f623f80,0xbef10000,0xbe95bf35,0x3f753f35,
0x3dc93f0e,0xbf7fbf55,0x3f223e48,0x3f463f7b,0xbf46bec4,0xbf22bf6d,0x3f7f3f6d,0xbdc93ec4,0xbf75bf7b,0x3e95be48,0x3ef13f55,0xbf62bf0e,
0x3f553f80,0xbf0e0000,0x3f0e0000,0x3f553f80,0xbe483ec4,0xbf7bbf6d,0x3f7b3f6d,0xbe483ec4,0xbf7bbf35,0xbe48bf35,0x3e483f35,0xbf7bbf35,
0xbf0ebf6d,0x3f553ec4,0xbf55bec4,0xbf0ebf6d,0x3f463f80,0xbf220000,0x3f7f3f35,0x3dc93f35,0xbef13e48,0xbf62bf7b,0x3e953f55,0xbf75bf0e,
0xbf75bf6d,0x3e95bec4,0xbf62bec4,0xbef1bf6d,0x3dc9bf0e,0x3f7f3f55,0xbf22bf7b,0x3f463e48,0x3f353f80,0xbf350000,0x3f353f80,0xbf350000,
0xbf350000,0xbf35bf80,0xbf350000,0xbf35bf80,0xbf35bf80,0x3f350000,0xbf35bf80,0x3f350000,0x3f350000,0x3f353f80,0x3f350000,0x3f353f80,
0x3f223f80,0xbf460000,0xbdc93f35,0xbf7fbf35,0xbf62be48,0xbef1bf7b,0xbf75bf55,0x3e95bf0e,0xbe95bf6d,0x3f753ec4,0x3ef1bec4,0x3f623f6d,
0x3f7f3f0e,0x3dc93f55,0x3f463f7b,0xbf223e48,0x3f0e3f80,0xbf550000,0xbf550000,0xbf0ebf80,0xbf7bbec4,0xbe48bf6d,0xbe48bf6d,0x3f7b3ec4,
0x3e48bf35,0x3f7b3f35,0x3f7b3f35,0xbe483f35,0x3f553f6d,0xbf0e3ec4,0xbf0e3ec4,0xbf55bf6d,0x3ef13f80,0xbf620000,0xbf75bf35,0x3e95bf35,
0xbf7fbf0e,0x3dc9bf55,0x3f46be48,0x3f223f7b,0x3f22bec4,0x3f463f6d,0x3dc93f6d,0xbf7fbec4,0x3e953f7b,0xbf75be48,0xbf62bf55,0x3ef1bf0e,
0x3ec43f80,0xbf6d0000,0xbec4bf80,0x3f6d0000,0xbf6dbf35,0x3ec4bf35,0x3f6d3f35,0xbec43f35,0x3f6d0000,0x3ec43f80,0xbf6d0000,0xbec4bf80,
0xbec43f35,0xbf6dbf35,0x3ec4bf35,0x3f6d3f35,0x3e953f80,0xbf750000,0x3ef1bf35,0x3f623f35,0xbf46bf55,0x3f22bf0e,0x3dc93f7b,0xbf7fbe48,
0x3f7f3ec4,0xbdc93f6d,0xbf22bf6d,0x3f46bec4,0xbf623e48,0xbef1bf7b,0x3f753f0e,0xbe953f55,0x3e483f80,0xbf7b0000,0x3f7b0000,0x3e483f80,
0xbf0ebf6d,0x3f55bec4,0xbf553ec4,0xbf0ebf6d,0x3f553f35,0xbf0e3f35,0x3f0ebf35,0x3f553f35,0xbf7bbec4,0x3e48bf6d,0xbe483f6d,0xbf7bbec4,
0x3dc93f80,0xbf7f0000,0x3f463f35,0xbf223f35,0xbe95bf7b,0x3f75be48,0xbf62bf0e,0x3ef1bf55,0x3ef13f6d,0xbf623ec4,0x3f753ec4,0xbe953f6d,
0xbf22bf55,0x3f46bf0e,0xbf7fbe48,0x3dc9bf7b,0x3f80,0xbf800000,0x3f80,0xbf800000,0xbf80,0x3f800000,0xbf80,0x3f800000,
0x3f80,0xbf800000,0x3f80,0xbf800000,0xbf80,0x3f800000,0xbf80,0x3f800000,0xbdc93f80,0xbf7f0000,0xbf463f35,0xbf22bf35,
0x3e95bf7b,0x3f753e48,0x3f62bf0e,0x3ef13f55,0xbef13f6d,0xbf62bec4,0xbf753ec4,0xbe95bf6d,0x3f22bf55,0x3f463f0e,0x3f7fbe48,0x3dc93f7b,
0xbe483f80,0xbf7b0000,0xbf7b0000,0x3e48bf80,0x3f0ebf6d,0x3f553ec4,0x3f553ec4,0xbf0e3f6d,0xbf553f35,0xbf0ebf35,0xbf0ebf35,0x3f55bf35,
0x3f7bbec4,0x3e483f6d,0x3e483f6d,0xbf7b3ec4,0xbe953f80,0xbf750000,0xbef1bf35,0x3f62bf35,0x3f46bf55,0x3f223f0e,0xbdc93f7b,0xbf7f3e48,
0xbf7f3ec4,0xbdc9bf6d,0x3f22bf6d,0x3f463ec4,0x3f623e48,0xbef13f7b,0xbf753f0e,0xbe95bf55,0xbec43f80,0xbf6d0000,0x3ec4bf80,0x3f6d0000,
0x3f6dbf35,0x3ec43f35,0xbf6d3f35,0xbec4bf35,0xbf6d0000,0x3ec4bf80,0x3f6d0000,0xbec43f80,0x3ec43f35,0xbf6d3f35,0xbec4bf35,0x3f6dbf35,
0xbef13f80,0xbf620000,0x3f75bf35,0x3e953f35,0x3f7fbf0e,0x3dc93f55,0xbf46be48,0x3f22bf7b,0xbf22bec4,0x3f46bf6d,0xbdc93f6d,0xbf7f3ec4,
0xbe953f7b,0xbf753e48,0x3f62bf55,0x3ef13f0e,0xbf0e3f80,0xbf550000,0x3f550000,0xbf0e3f80,0x3f7bbec4,0xbe483f6d,0x3e48bf6d,0x3f7bbec4,
0xbe48bf35,0x3f7bbf35,0xbf7b3f35,0xbe48bf35,0xbf553f6d,0xbf0ebec4,0x3f0e3ec4,0xbf553f6d,0xbf223f80,0xbf460000,0x3dc93f35,0xbf7f3f35,
0x3f62be48,0xbef13f7b,0x3f75bf55,0x3e953f0e,0x3e95bf6d,0x3f75bec4,0xbef1bec4,0x3f62bf6d,0xbf7f3f0e,0x3dc9bf55,0xbf463f7b,0xbf22be48,
0xbf353f80,0xbf350000,0xbf353f80,0xbf350000,0x3f350000,0xbf353f80,0x3f350000,0xbf353f80,0x3f35bf80,0x3f350000,0x3f35bf80,0x3f350000,
0xbf350000,0x3f35bf80,0xbf350000,0x3f35bf80,0xbf463f80,0xbf220000,0xbf7f3f35,0x3dc9bf35,0x3ef13e48,0xbf623f7b,0xbe953f55,0xbf753f0e,
0x3f75bf6d,0x3e953ec4,0x3f62bec4,0xbef13f6d,0xbdc9bf0e,0x3f7fbf55,0x3f22bf7b,0x3f46be48,0xbf553f80,0xbf0e0000,0xbf0e0000,0x3f55bf80,
0x3e483ec4,0xbf7b3f6d,0xbf7b3f6d,0xbe48bec4,0x3f7bbf35,0xbe483f35,0xbe483f35,0xbf7b3f35,0x3f0ebf6d,0x3f55bec4,0x3f55bec4,0xbf0e3f6d,
0xbf623f80,0xbef10000,0x3e95bf35,0x3f75bf35,0xbdc93f0e,0xbf7f3f55,0xbf223e48,0x3f46bf7b,0x3f46bec4,0xbf223f6d,0xbf7f3f6d,0xbdc9bec4,
0x3f75bf7b,0x3e953e48,0xbef13f55,0xbf623f0e,0xbf6d3f80,0xbec40000,0x3f6dbf80,0x3ec40000,0xbec43f35,0xbf6d3f35,0x3ec4bf35,0x3f6dbf35,
0x3ec40000,0xbf6d3f80,0xbec40000,0x3f6dbf80,0x3f6dbf35,0xbec43f35,0xbf6d3f35,0x3ec4bf35,0xbf753f80,0xbe950000,0x3f62bf35,0xbef13f35,
0xbf223f55,0xbf463f0e,0x3f7fbf7b,0x3dc93e48,0xbdc93ec4,0xbf7f3f6d,0x3f46bf6d,0x3f22bec4,0x3ef1be48,0xbf623f7b,0x3e95bf0e,0x3f75bf55,
0xbf7b3f80,0xbe480000,0x3e480000,0xbf7b3f80,0xbf553f6d,0xbf0e3ec4,0x3f0ebec4,0xbf553f6d,0xbf0e3f35,0xbf553f35,0x3f55bf35,0xbf0e3f35,
0xbe483ec4,0xbf7b3f6d,0x3f7bbf6d,0xbe483ec4,0xbf7f3f80,0xbdc90000,0xbf223f35,0xbf463f35,0xbf753f7b,0xbe953e48,0xbef13f0e,0xbf623f55,
0xbf623f6d,0xbef13ec4,0xbe953ec4,0xbf753f6d,0xbf463f55,0xbf223f0e,0xbdc93e48,0xbf7f3f7b,0x3f803f80,0xbf803f80,0x3f803f80,0xbf803f80,
0x3f803f80,0xbf803f80,0x3f803f80,0xbf803f80,0x3f803f80,0xbf803f80,0x3f803f80,0xbf803f80,0x3f803f80,0xbf803f80,0x3f803f80,0xbf803f80,
0xbdc90000,0xbf7fbf80,0xbf46bf35,0xbf22bf35,0xbe95be48,0xbf75bf7b,0xbf62bf55,0xbef1bf0e,0xbef1bec4,0xbf62bf6d,0xbf75bf6d,0xbe95bec4,
0xbf22bf0e,0xbf46bf55,0xbf7fbf7b,0xbdc9be48,0xbf7bbf80,0x3e480000,0x3e480000,0x3f7b3f80,0xbf55bf6d,0x3f0e3ec4,0x3f0e3ec4,0x3f553f6d,
0xbf0ebf35,0x3f553f35,0x3f553f35,0x3f0e3f35,0xbe48bec4,0x3f7b3f6d,0x3f7b3f6d,0x3e483ec4,0x3e950000,0x3f753f80,0x3ef13f35,0xbf62bf35,
0x3f463f0e,0x3f223f55,0xbdc93e48,0xbf7fbf7b,0x3f7f3f6d,0x3dc93ec4,0xbf22bec4,0xbf46bf6d,0x3f623f7b,0xbef1be48,0xbf75bf55,0xbe95bf0e,
0x3f6d3f80,0xbec40000,0xbf6dbf80,0x3ec40000,0x3ec43f35,0xbf6dbf35,0xbec4bf35,0x3f6d3f35,0xbec40000,0xbf6dbf80,0x3ec40000,0x3f6d3f80,
0xbf6dbf35,0xbec4bf35,0x3f6d3f35,0x3ec43f35,0xbef10000,0xbf62bf80,0x3f753f35,0x3e953f35,0xbf7fbf55,0xbdc9bf0e,0x3f463f7b,0xbf22be48,
0xbf22bf6d,0x3f463ec4,0xbdc93ec4,0xbf7fbf6d,0x3e95be48,0x3f753f7b,0xbf62bf0e,0xbef1bf55,0xbf55bf80,0x3f0e0000,0xbf0e0000,0xbf55bf80,
0x3e48bec4,0x3f7b3f6d,0xbf7bbf6d,0x3e48bec4,0x3f7b3f35,0x3e483f35,0xbe48bf35,0x3f7b3f35,0x3f0e3f6d,0xbf55bec4,0x3f553ec4,0x3f0e3f6d,
0x3f220000,0x3f463f80,0xbdc9bf35,0x3f7f3f35,0x3f623f7b,0xbef13e48,0x3f753f0e,0x3e953f55,0xbe953ec4,0xbf75bf6d,0x3ef13f6d,0xbf62bec4,
0xbf7fbf55,0x3dc9bf0e,0xbf46be48,0xbf22bf7b,0x3f353f80,0xbf350000,0x3f353f80,0xbf350000,0xbf350000,0xbf35bf80,0xbf350000,0xbf35bf80,
0xbf35bf80,0x3f350000,0xbf35bf80,0x3f350000,0x3f350000,0x3f353f80,0x3f350000,0x3f353f80,0xbf460000,0xbf22bf80,0xbf7fbf35,0x3dc9bf35,
0xbef1bf7b,0x3f623e48,0x3e95bf0e,0x3f753f55,0x3f753ec4,0x3e953f6d,0x3f623f6d,0xbef13ec4,0x3dc93f55,0xbf7fbf0e,0xbf223e48,0xbf46bf7b,
0xbf0ebf80,0x3f550000,0x3f550000,0x3f0e3f80,0x3f7b3ec4,0x3e483f6d,0x3e483f6d,0xbf7bbec4,0xbe483f35,0xbf7bbf35,0xbf7bbf35,0x3e48bf35,
0xbf55bf6d,0x3f0ebec4,0x3f0ebec4,0x3f553f6d,0x3f620000,0x3ef13f80,0xbe953f35,0xbf75bf35,0xbdc93f55,0xbf7fbf0e,0xbf22bf7b,0x3f46be48,
0xbf46bf6d,0x3f22bec4,0x3f7f3ec4,0x3dc93f6d,0x3f753e48,0x3e953f7b,0xbef13f0e,0xbf62bf55,0x3ec43f80,0xbf6d0000,0xbec4bf80,0x3f6d0000,
0xbf6dbf35,0x3ec4bf35,0x3f6d3f35,0xbec43f35,0x3f6d0000,0x3ec43f80,0xbf6d0000,0xbec4bf80,0xbec43f35,0xbf6dbf35,0x3ec4bf35,0x3f6d3f35,
0xbf750000,0xbe95bf80,0x3f623f35,0xbef13f35,0x3f22bf0e,0x3f463f55,0xbf7fbe48,0xbdc9bf7b,0xbdc93f6d,0xbf7fbec4,0x3f46bec4,0x3f223f6d,
0xbef1bf7b,0x3f62be48,0xbe953f55,0xbf75bf0e,0xbe48bf80,0x3f7b0000,0xbf7b0000,0xbe48bf80,0x3f0e3f6d,0xbf553ec4,0x3f55bec4,0x3f0e3f6d,
0xbf55bf35,0x3f0ebf35,0xbf0e3f35,0xbf55bf35,0x3f7b3ec4,0xbe483f6d,0x3e48bf6d,0x3f7b3ec4,0x3f7f0000,0x3dc93f80,0x3f22bf35,0x3f463f35,
0xbf753e48,0xbe95bf7b,0xbef13f55,0xbf62bf0e,0x3f62bec4,0x3ef13f6d,0x3e95bf6d,0x3f753ec4,0xbf463f0e,0xbf22bf55,0xbdc93f7b,0xbf7fbe48,
0x3f80,0xbf800000,0x3f80,0xbf800000,0xbf80,0x3f800000,0xbf80,0x3f800000,0x3f80,0xbf800000,0x3f80,0xbf800000,
0xbf80,0x3f800000,0xbf80,0x3f800000,0xbf7f0000,0x3dc9bf80,0xbf22bf35,0x3f46bf35,0x3f753e48,0xbe953f7b,0x3ef13f55,0xbf623f0e,
0xbf62bec4,0x3ef1bf6d,0xbe95bf6d,0x3f75bec4,0x3f463f0e,0xbf223f55,0x3dc93f7b,0xbf7f3e48,0x3e48bf80,0x3f7b0000,0x3f7b0000,0xbe483f80,
0xbf0e3f6d,0xbf55bec4,0xbf55bec4,0x3f0ebf6d,0x3f55bf35,0x3f0e3f35,0x3f0e3f35,0xbf553f35,0xbf7b3ec4,0xbe48bf6d,0xbe48bf6d,0x3f7bbec4,
0x3f750000,0xbe953f80,0xbf623f35,0xbef1bf35,0xbf22bf0e,0x3f46bf55,0x3f7fbe48,0xbdc93f7b,0x3dc93f6d,0xbf7f3ec4,0xbf46bec4,0x3f22bf6d,
0x3ef1bf7b,0x3f623e48,0x3e953f55,0xbf753f0e,0xbec43f80,0xbf6d0000,0x3ec4bf80,0x3f6d0000,0x3f6dbf35,0x3ec43f35,0xbf6d3f35,0xbec4bf35,
0xbf6d0000,0x3ec4bf80,0x3f6d0000,0xbec43f80,0x3ec43f35,0xbf6d3f35,0xbec4bf35,0x3f6dbf35,0xbf620000,0x3ef1bf80,0x3e953f35,0xbf753f35,
0x3dc93f55,0xbf7f3f0e,0x3f22bf7b,0x3f463e48,0x3f46bf6d,0x3f223ec4,0xbf7f3ec4,0x3dc9bf6d,0xbf753e48,0x3e95bf7b,0x3ef13f0e,0xbf623f55,
0x3f0ebf80,0x3f550000,0xbf550000,0x3f0ebf80,0xbf7b3ec4,0x3e48bf6d,0xbe483f6d,0xbf7b3ec4,0x3e483f35,0xbf7b3f35,0x3f7bbf35,0x3e483f35,
0x3f55bf6d,0x3f0e3ec4,0xbf0ebec4,0x3f55bf6d,0x3f460000,0xbf223f80,0x3f7fbf35,0x3dc93f35,0x3ef1bf7b,0x3f62be48,0xbe95bf0e,0x3f75bf55,
0xbf753ec4,0x3e95bf6d,0xbf623f6d,0xbef1bec4,0xbdc93f55,0xbf7f3f0e,0x3f223e48,0xbf463f7b,0xbf353f80,0xbf350000,0xbf353f80,0xbf350000,
0x3f350000,0xbf353f80,0x3f350000,0xbf353f80,0x3f35bf80,0x3f350000,0x3f35bf80,0x3f350000,0xbf350000,0x3f35bf80,0xbf350000,0x3f35bf80,
0xbf220000,0x3f46bf80,0x3dc9bf35,0x3f7fbf35,0xbf623f7b,0xbef1be48,0xbf753f0e,0x3e95bf55,0x3e953ec4,0xbf753f6d,0xbef13f6d,0xbf623ec4,
0x3f7fbf55,0x3dc93f0e,0x3f46be48,0xbf223f7b,0x3f55bf80,0x3f0e0000,0x3f0e0000,0xbf553f80,0xbe48bec4,0x3f7bbf6d,0x3f7bbf6d,0x3e483ec4,
0xbf7b3f35,0x3e48bf35,0x3e48bf35,0x3f7bbf35,0xbf0e3f6d,0xbf553ec4,0xbf553ec4,0x3f0ebf6d,0x3ef10000,0xbf623f80,0xbf753f35,0x3e95bf35,
0x3f7fbf55,0xbdc93f0e,0xbf463f7b,0xbf223e48,0x3f22bf6d,0x3f46bec4,0x3dc93ec4,0xbf7f3f6d,0xbe95be48,0x3f75bf7b,0x3f62bf0e,0xbef13f55,
0xbf6d3f80,0xbec40000,0x3f6dbf80,0x3ec40000,0xbec43f35,0xbf6d3f35,0x3ec4bf35,0x3f6dbf35,0x3ec40000,0xbf6d3f80,0xbec40000,0x3f6dbf80,
0x3f6dbf35,0xbec43f35,0xbf6d3f35,0x3ec4bf35,0xbe950000,0x3f75bf80,0xbef13f35,0xbf623f35,0xbf463f0e,0x3f22bf55,0x3dc93e48,0xbf7f3f7b,
0xbf7f3f6d,0x3dc9bec4,0x3f22bec4,0xbf463f6d,0xbf623f7b,0xbef13e48,0x3f75bf55,0xbe953f0e,0x3f7bbf80,0x3e480000,0xbe480000,0x3f7bbf80,
0x3f55bf6d,0x3f0ebec4,0xbf0e3ec4,0x3f55bf6d,0x3f0ebf35,0x3f55bf35,0xbf553f35,0x3f0ebf35,0x3e48bec4,0x3f7bbf6d,0xbf7b3f6d,0x3e48bec4,
0x3dc90000,0xbf7f3f80,0x3f46bf35,0xbf223f35,0x3e95be48,0xbf753f7b,0x3f62bf55,0xbef13f0e,0x3ef1bec4,0xbf623f6d,0x3f75bf6d,0xbe953ec4,
0x3f22bf0e,0xbf463f55,0x3f7fbf7b,0xbdc93e48,0x3f803f80,0xbf803f80,0x3f803f80,0xbf803f80,0x3f803f80,0xbf803f80,0x3f803f80,0xbf803f80,
0x3f803f80,0xbf803f80,0x3f803f80,0xbf803f80,0x3f803f80,0xbf803f80,0x3f803f80,0xbf803f80,0xbf7fbf80,0x3dc90000,0xbf22bf35,0x3f463f35,
0xbf75bf7b,0x3e953e48,0xbef1bf0e,0x3f623f55,0xbf62bf6d,0x3ef13ec4,0xbe95bec4,0x3f753f6d,0xbf46bf55,0x3f223f0e,0xbdc9be48,0x3f7f3f7b,
0x3f7b3f80,0xbe480000,0xbe480000,0xbf7bbf80,0x3f553f6d,0xbf0ebec4,0xbf0ebec4,0xbf55bf6d,0x3f0e3f35,0xbf55bf35,0xbf55bf35,0xbf0ebf35,
0x3e483ec4,0xbf7bbf6d,0xbf7bbf6d,0xbe48bec4,0xbf75bf80,0x3e950000,0x3f623f35,0x3ef13f35,0xbf22bf55,0x3f463f0e,0x3f7f3f7b,0xbdc93e48,
0xbdc9bec4,0x3f7f3f6d,0x3f463f6d,0xbf22bec4,0x3ef13e48,0x3f623f7b,0x3e953f0e,0xbf75bf55,0x3f6d3f80,0xbec40000,0xbf6dbf80,0x3ec40000,
0x3ec43f35,0xbf6dbf35,0xbec4bf35,0x3f6d3f35,0xbec40000,0xbf6dbf80,0x3ec40000,0x3f6d3f80,0xbf6dbf35,0xbec4bf35,0x3f6d3f35,0x3ec43f35,
0xbf62bf80,0x3ef10000,0x3e953f35,0xbf75bf35,0xbdc9bf0e,0x3f7f3f55,0xbf22be48,0xbf46bf7b,0x3f463ec4,0x3f223f6d,0xbf7fbf6d,0x3dc9bec4,
0x3f753f7b,0xbe953e48,0xbef1bf55,0x3f623f0e,0x3f553f80,0xbf0e0000,0x3f0e0000,0x3f553f80,0xbe483ec4,0xbf7bbf6d,0x3f7b3f6d,0xbe483ec4,
0xbf7bbf35,0xbe48bf35,0x3e483f35,0xbf7bbf35,0xbf0ebf6d,0x3f553ec4,0xbf55bec4,0xbf0ebf6d,0xbf46bf80,0x3f220000,0xbf7fbf35,0xbdc9bf35,
0x3ef1be48,0x3f623f7b,0xbe95bf55,0x3f753f0e,0x3f753f6d,0xbe953ec4,0x3f623ec4,0x3ef13f6d,0xbdc93f0e,0xbf7fbf55,0x3f223f7b,0xbf46be48,
0x3f353f80,0xbf350000,0x3f353f80,0xbf350000,0xbf350000,0xbf35bf80,0xbf350000,0xbf35bf80,0xbf35bf80,0x3f350000,0xbf35bf80,0x3f350000,
0x3f350000,0x3f353f80,0x3f350000,0x3f353f80,0xbf22bf80,0x3f460000,0x3dc9bf35,0x3f7f3f35,0x3f623e48,0x3ef13f7b,0x3f753f55,0xbe953f0e,
0x3e953f6d,0xbf75bec4,0xbef13ec4,0xbf62bf6d,0xbf7fbf0e,0xbdc9bf55,0xbf46bf7b,0x3f22be48,0x3f0e3f80,0xbf550000,0xbf550000,0xbf0ebf80,
0xbf7bbec4,0xbe48bf6d,0xbe48bf6d,0x3f7b3ec4,0x3e48bf35,0x3f7b3f35,0x3f7b3f35,0xbe483f35,0x3f553f6d,0xbf0e3ec4,0xbf0e3ec4,0xbf55bf6d,
0xbef1bf80,0x3f620000,0x3f753f35,0xbe953f35,0x3f7f3f0e,0xbdc93f55,0xbf463e48,0xbf22bf7b,0xbf223ec4,0xbf46bf6d,0xbdc9bf6d,0x3f7f3ec4,
0xbe95bf7b,0x3f753e48,0x3f623f55,0xbef13f0e,0x3ec43f80,0xbf6d0000,0xbec4bf80,0x3f6d0000,0xbf6dbf35,0x3ec4bf35,0x3f6d3f35,0xbec43f35,
0x3f6d0000,0x3ec43f80,0xbf6d0000,0xbec4bf80,0xbec43f35,0xbf6dbf35,0x3ec4bf35,0x3f6d3f35,0xbe95bf80,0x3f750000,0xbef13f35,0xbf62bf35,
0x3f463f55,0xbf223f0e,0xbdc9bf7b,0x3f7f3e48,0xbf7fbec4,0x3dc9bf6d,0x3f223f6d,0xbf463ec4,0x3f62be48,0x3ef13f7b,0xbf75bf0e,0x3e95bf55,
0x3e483f80,0xbf7b0000,0x3f7b0000,0x3e483f80,0xbf0ebf6d,0x3f55bec4,0xbf553ec4,0xbf0ebf6d,0x3f553f35,0xbf0e3f35,0x3f0ebf35,0x3f553f35,
0xbf7bbec4,0x3e48bf6d,0xbe483f6d,0xbf7bbec4,0xbdc9bf80,0x3f7f0000,0xbf46bf35,0x3f22bf35,0x3e953f7b,0xbf753e48,0x3f623f0e,0xbef13f55,
0xbef1bf6d,0x3f62bec4,0xbf75bec4,0x3e95bf6d,0x3f223f55,0xbf463f0e,0x3f7f3e48,0xbdc93f7b,0x3f80,0xbf800000,0x3f80,0xbf800000,
0xbf80,0x3f800000,0xbf80,0x3f800000,0x3f80,0xbf800000,0x3f80,0xbf800000,0xbf80,0x3f800000,0xbf80,0x3f800000,
0x3dc9bf80,0x3f7f0000,0x3f46bf35,0x3f223f35,0xbe953f7b,0xbf75be48,0xbf623f0e,0xbef1bf55,0x3ef1bf6d,0x3f623ec4,0x3f75bec4,0x3e953f6d,
0xbf223f55,0xbf46bf0e,0xbf7f3e48,0xbdc9bf7b,0xbe483f80,0xbf7b0000,0xbf7b0000,0x3e48bf80,0x3f0ebf6d,0x3f553ec4,0x3f553ec4,0xbf0e3f6d,
0xbf553f35,0xbf0ebf35,0xbf0ebf35,0x3f55bf35,0x3f7bbec4,0x3e483f6d,0x3e483f6d,0xbf7b3ec4,0x3e95bf80,0x3f750000,0x3ef13f35,0xbf623f35,
0xbf463f55,0xbf22bf0e,0x3dc9bf7b,0x3f7fbe48,0x3f7fbec4,0x3dc93f6d,0xbf223f6d,0xbf46bec4,0xbf62be48,0x3ef1bf7b,0x3f75bf0e,0x3e953f55,
0xbec43f80,0xbf6d0000,0x3ec4bf80,0x3f6d0000,0x3f6dbf35,0x3ec43f35,0xbf6d3f35,0xbec4bf35,0xbf6d0000,0x3ec4bf80,0x3f6d0000,0xbec43f80,
0x3ec43f35,0xbf6d3f35,0xbec4bf35,0x3f6dbf35,0x3ef1bf80,0x3f620000,0xbf753f35,0xbe95bf35,0xbf7f3f0e,0xbdc9bf55,0x3f463e48,0xbf223f7b,
0x3f223ec4,0xbf463f6d,0x3dc9bf6d,0x3f7fbec4,0x3e95bf7b,0x3f75be48,0xbf623f55,0xbef1bf0e,0xbf0e3f80,0xbf550000,0x3f550000,0xbf0e3f80,
0x3f7bbec4,0xbe483f6d,0x3e48bf6d,0x3f7bbec4,0xbe48bf35,0x3f7bbf35,0xbf7b3f35,0xbe48bf35,0xbf553f6d,0xbf0ebec4,0x3f0e3ec4,0xbf553f6d,
0x3f22bf80,0x3f460000,0xbdc9bf35,0x3f7fbf35,0xbf623e48,0x3ef1bf7b,0xbf753f55,0xbe95bf0e,0xbe953f6d,0xbf753ec4,0x3ef13ec4,0xbf623f6d,
0x3f7fbf0e,0xbdc93f55,0x3f46bf7b,0x3f223e48,0xbf353f80,0xbf350000,0xbf353f80,0xbf350000,0x3f350000,0xbf353f80,0x3f350000,0xbf353f80,
0x3f35bf80,0x3f350000,0x3f35bf80,0x3f350000,0xbf350000,0x3f35bf80,0xbf350000,0x3f35bf80,0x3f46bf80,0x3f220000,0x3f7fbf35,0xbdc93f35,
0xbef1be48,0x3f62bf7b,0x3e95bf55,0x3f75bf0e,0xbf753f6d,0xbe95bec4,0xbf623ec4,0x3ef1bf6d,0x3dc93f0e,0xbf7f3f55,0xbf223f7b,0xbf463e48,
0xbf553f80,0xbf0e0000,0xbf0e0000,0x3f55bf80,0x3e483ec4,0xbf7b3f6d,0xbf7b3f6d,0xbe48bec4,0x3f7bbf35,0xbe483f35,0xbe483f35,0xbf7b3f35,
0x3f0ebf6d,0x3f55bec4,0x3f55bec4,0xbf0e3f6d,0x3f62bf80,0x3ef10000,0xbe953f35,0xbf753f35,0x3dc9bf0e,0x3f7fbf55,0x3f22be48,0xbf463f7b,
0xbf463ec4,0x3f22bf6d,0x3f7fbf6d,0x3dc93ec4,0xbf753f7b,0xbe95be48,0x3ef1bf55,0x3f62bf0e,0xbf6d3f80,0xbec40000,0x3f6dbf80,0x3ec40000,
0xbec43f35,0xbf6d3f35,0x3ec4bf35,0x3f6dbf35,0x3ec40000,0xbf6d3f80,0xbec40000,0x3f6dbf80,0x3f6dbf35,0xbec43f35,0xbf6d3f35,0x3ec4bf35,
0x3f75bf80,0x3e950000,0xbf623f35,0x3ef1bf35,0x3f22bf55,0x3f46bf0e,0xbf7f3f7b,0xbdc9be48,0x3dc9bec4,0x3f7fbf6d,0xbf463f6d,0xbf223ec4,
0xbef13e48,0x3f62bf7b,0xbe953f0e,0xbf753f55,0xbf7b3f80,0xbe480000,0x3e480000,0xbf7b3f80,0xbf553f6d,0xbf0e3ec4,0x3f0ebec4,0xbf553f6d,
0xbf0e3f35,0xbf553f35,0x3f55bf35,0xbf0e3f35,0xbe483ec4,0xbf7b3f6d,0x3f7bbf6d,0xbe483ec4,0x3f7fbf80,0x3dc90000,0x3f22bf35,0x3f46bf35,
0x3f75bf7b,0x3e95be48,0x3ef1bf0e,0x3f62bf55,0x3f62bf6d,0x3ef1bec4,0x3e95bec4,0x3f75bf6d,0x3f46bf55,0x3f22bf0e,0x3dc9be48,0x3f7fbf7b,
0x3f803f80,0xbf803f80,0x3f803f80,0xbf803f80,0x3f803f80,0xbf803f80,0x3f803f80,0xbf803f80,0x3f803f80,0xbf803f80,0x3f803f80,0xbf803f80,
0x3f803f80,0xbf803f80,0x3f803f80,0xbf803f80,0x3dc90000,0x3f7f3f80,0x3f463f35,0x3f223f35,0x3e953e48,0x3f753f7b,0x3f623f55,0x3ef13f0e,
0x3ef13ec4,0x3f623f6d,0x3f753f6d,0x3e953ec4,0x3f223f0e,0x3f463f55,0x3f7f3f7b,0x3dc93e48,0xbf7bbf80,0x3e480000,0x3e480000,0x3f7b3f80,
0xbf55bf6d,0x3f0e3ec4,0x3f0e3ec4,0x3f553f6d,0xbf0ebf35,0x3f553f35,0x3f553f35,0x3f0e3f35,0xbe48bec4,0x3f7b3f6d,0x3f7b3f6d,0x3e483ec4,
0xbe950000,0xbf75bf80,0xbef1bf35,0x3f623f35,0xbf46bf0e,0xbf22bf55,0x3dc9be48,0x3f7f3f7b,0xbf7fbf6d,0xbdc9bec4,0x3f223ec4,0x3f463f6d,
0xbf62bf7b,0x3ef13e48,0x3f753f55,0x3e953f0e,0x3f6d3f80,0xbec40000,0xbf6dbf80,0x3ec40000,0x3ec43f35,0xbf6dbf35,0xbec4bf35,0x3f6d3f35,
0xbec40000,0xbf6dbf80,0x3ec40000,0x3f6d3f80,0xbf6dbf35,0xbec4bf35,0x3f6d3f35,0x3ec43f35,0x3ef10000,0x3f623f80,0xbf75bf35,0xbe95bf35,
0x3f7f3f55,0x3dc93f0e,0xbf46bf7b,0x3f223e48,0x3f223f6d,0xbf46bec4,0x3dc9bec4,0x3f7f3f6d,0xbe953e48,0xbf75bf7b,0x3f623f0e,0x3ef13f55,
0xbf55bf80,0x3f0e0000,0xbf0e0000,0xbf55bf80,0x3e48bec4,0x3f7b3f6d,0xbf7bbf6d,0x3e48bec4,0x3f7b3f35,0x3e483f35,0xbe48bf35,0x3f7b3f35,
0x3f0e3f6d,0xbf55bec4,0x3f553ec4,0x3f0e3f6d,0xbf220000,0xbf46bf80,0x3dc93f35,0xbf7fbf35,0xbf62bf7b,0x3ef1be48,0xbf75bf0e,0xbe95bf55,
0x3e95bec4,0x3f753f6d,0xbef1bf6d,0x3f623ec4,0x3f7f3f55,0xbdc93f0e,0x3f463e48,0x3f223f7b,0x3f353f80,0xbf350000,0x3f353f80,0xbf350000,
0xbf350000,0xbf35bf80,0xbf350000,0xbf35bf80,0xbf35bf80,0x3f350000,0xbf35bf80,0x3f350000,0x3f350000,0x3f353f80,0x3f350000,0x3f353f80,
0x3f460000,0x3f223f80,0x3f7f3f35,0xbdc93f35,0x3ef13f7b,0xbf62be48,0xbe953f0e,0xbf75bf55,0xbf75bec4,0xbe95bf6d,0xbf62bf6d,0x3ef1bec4,
0xbdc9bf55,0x3f7f3f0e,0x3f22be48,0x3f463f7b,0xbf0ebf80,0x3f550000,0x3f550000,0x3f0e3f80,0x3f7b3ec4,0x3e483f6d,0x3e483f6d,0xbf7bbec4,
0xbe483f35,0xbf7bbf35,0xbf7bbf35,0x3e48bf35,0xbf55bf6d,0x3f0ebec4,0x3f0ebec4,0x3f553f6d,0xbf620000,0xbef1bf80,0x3e95bf35,0x3f753f35,
0x3dc9bf55,0x3f7f3f0e,0x3f223f7b,0xbf463e48,0x3f463f6d,0xbf223ec4,0xbf7fbec4,0xbdc9bf6d,0xbf75be48,0xbe95bf7b,0x3ef1bf0e,0x3f623f55,
0x3ec43f80,0xbf6d0000,0xbec4bf80,0x3f6d0000,0xbf6dbf35,0x3ec4bf35,0x3f6d3f35,0xbec43f35,0x3f6d0000,0x3ec43f80,0xbf6d0000,0xbec4bf80,
0xbec43f35,0xbf6dbf35,0x3ec4bf35,0x3f6d3f35,0x3f750000,0x3e953f80,0xbf62bf35,0x3ef1bf35,0xbf223f0e,0xbf46bf55,0x3f7f3e48,0x3dc93f7b,
0x3dc9bf6d,0x3f7f3ec4,0xbf463ec4,0xbf22bf6d,0x3ef13f7b,0xbf623e48,0x3e95bf55,0x3f753f0e,0xbe48bf80,0x3f7b0000,0xbf7b0000,0xbe48bf80,
0x3f0e3f6d,0xbf553ec4,0x3f55bec4,0x3f0e3f6d,0xbf55bf35,0x3f0ebf35,0xbf0e3f35,0xbf55bf35,0x3f7b3ec4,0xbe483f6d,0x3e48bf6d,0x3f7b3ec4,
0xbf7f0000,0xbdc9bf80,0xbf223f35,0xbf46bf35,0x3f75be48,0x3e953f7b,0x3ef1bf55,0x3f623f0e,0xbf623ec4,0xbef1bf6d,0xbe953f6d,0xbf75bec4,
0x3f46bf0e,0x3f223f55,0x3dc9bf7b,0x3f7f3e48,0x3f80,0xbf800000,0x3f80,0xbf800000,0xbf80,0x3f800000,0xbf80,0x3f800000,
0x3f80,0xbf800000,0x3f80,0xbf800000,0xbf80,0x3f800000,0xbf80,0x3f800000,0x3f7f0000,0xbdc93f80,0x3f223f35,0xbf463f35,
0xbf75be48,0x3e95bf7b,0xbef1bf55,0x3f62bf0e,0x3f623ec4,0xbef13f6d,0x3e953f6d,0xbf753ec4,0xbf46bf0e,0x3f22bf55,0xbdc9bf7b,0x3f7fbe48,
0x3e48bf80,0x3f7b0000,0x3f7b0000,0xbe483f80,0xbf0e3f6d,0xbf55bec4,0xbf55bec4,0x3f0ebf6d,0x3f55bf35,0x3f0e3f35,0x3f0e3f35,0xbf553f35,
0xbf7b3ec4,0xbe48bf6d,0xbe48bf6d,0x3f7bbec4,0xbf750000,0x3e95bf80,0x3f62bf35,0x3ef13f35,0x3f223f0e,0xbf463f55,0xbf7f3e48,0x3dc9bf7b,
0xbdc9bf6d,0x3f7fbec4,0x3f463ec4,0xbf223f6d,0xbef13f7b,0xbf62be48,0xbe95bf55,0x3f75bf0e,0xbec43f80,0xbf6d0000,0x3ec4bf80,0x3f6d0000,
0x3f6dbf35,0x3ec43f35,0xbf6d3f35,0xbec4bf35,0xbf6d0000,0x3ec4bf80,0x3f6d0000,0xbec43f80,0x3ec43f35,0xbf6d3f35,0xbec4bf35,0x3f6dbf35,
0x3f620000,0xbef13f80,0xbe95bf35,0x3f75bf35,0xbdc9bf55,0x3f7fbf0e,0xbf223f7b,0xbf46be48,0xbf463f6d,0xbf22bec4,0x3f7fbec4,0xbdc93f6d,
0x3f75be48,0xbe953f7b,0xbef1bf0e,0x3f62bf55,0x3f0ebf80,0x3f550000,0xbf550000,0x3f0ebf80,0xbf7b3ec4,0x3e48bf6d,0xbe483f6d,0xbf7b3ec4,
0x3e483f35,0xbf7b3f35,0x3f7bbf35,0x3e483f35,0x3f55bf6d,0x3f0e3ec4,0xbf0ebec4,0x3f55bf6d,0xbf460000,0x3f22bf80,0xbf7f3f35,0xbdc9bf35,
0xbef13f7b,0xbf623e48,0x3e953f0e,0xbf753f55,0x3f75bec4,0xbe953f6d,0x3f62bf6d,0x3ef13ec4,0x3dc9bf55,0x3f7fbf0e,0xbf22be48,0x3f46bf7b,
0xbf353f80,0xbf350000,0xbf353f80,0xbf350000,0x3f350000,0xbf353f80,0x3f350000,0xbf353f80,0x3f35bf80,0x3f350000,0x3f35bf80,0x3f350000,
0xbf350000,0x3f35bf80,0xbf350000,0x3f35bf80,0x3f220000,0xbf463f80,0xbdc93f35,0xbf7f3f35,0x3f62bf7b,0x3ef13e48,0x3f75bf0e,0xbe953f55,
0xbe95bec4,0x3f75bf6d,0x3ef1bf6d,0x3f62bec4,0xbf7f3f55,0xbdc9bf0e,0xbf463e48,0x3f22bf7b,0x3f55bf80,0x3f0e0000,0x3f0e0000,0xbf553f80,
0xbe48bec4,0x3f7bbf6d,0x3f7bbf6d,0x3e483ec4,0xbf7b3f35,0x3e48bf35,0x3e48bf35,0x3f7bbf35,0xbf0e3f6d,0xbf553ec4,0xbf553ec4,0x3f0ebf6d,
0xbef10000,0x3f62bf80,0x3f75bf35,0xbe953f35,0xbf7f3f55,0x3dc9bf0e,0x3f46bf7b,0x3f22be48,0xbf223f6d,0xbf463ec4,0xbdc9bec4,0x3f7fbf6d,
0x3e953e48,0xbf753f7b,0xbf623f0e,0x3ef1bf55,0xbf6d3f80,0xbec40000,0x3f6dbf80,0x3ec40000,0xbec43f35,0xbf6d3f35,0x3ec4bf35,0x3f6dbf35,
0x3ec40000,0xbf6d3f80,0xbec40000,0x3f6dbf80,0x3f6dbf35,0xbec43f35,0xbf6d3f35,0x3ec4bf35,0x3e950000,0xbf753f80,0x3ef1bf35,0x3f62bf35,
0x3f46bf0e,0xbf223f55,0xbdc9be48,0x3f7fbf7b,0x3f7fbf6d,0xbdc93ec4,0xbf223ec4,0x3f46bf6d,0x3f62bf7b,0x3ef1be48,0xbf753f55,0x3e95bf0e,
0x3f7bbf80,0x3e480000,0xbe480000,0x3f7bbf80,0x3f55bf6d,0x3f0ebec4,0xbf0e3ec4,0x3f55bf6d,0x3f0ebf35,0x3f55bf35,0xbf553f35,0x3f0ebf35,
0x3e48bec4,0x3f7bbf6d,0xbf7b3f6d,0x3e48bec4,0xbdc90000,0x3f7fbf80,0xbf463f35,0x3f22bf35,0xbe953e48,0x3f75bf7b,0xbf623f55,0x3ef1bf0e,
0xbef13ec4,0x3f62bf6d,0xbf753f6d,0x3e95bec4,0xbf223f0e,0x3f46bf55,0xbf7f3f7b,0x3dc9be48,0x40003f80,0x3fb53f80,0x3f80,0xbfb53f80,
0x40004000,0xbfb50000,0x0,0xbfb5c000,0x40004000,0xbfb5c000,0x0,0x3fb50000,0x40004000,0x3fb50000,0x0,0x3fb54000,
0x3fff3f80,0x3fa23f80,0xbe49bf80,0xbfc6bf80,0x3ff53ffb,0xbfe2bec8,0xbf15bec8,0xbf71bffb,0x3fe23fed,0xbf15bfed,0xbf71bf44,0x3ff53f44,
0x3fc63fd5,0x3fff3f8e,0xbfa2bf8e,0x3e493fd5,0x3ffb3f80,0x3f8e3f80,0xbec83f80,0xbfd53f80,0x3fd53fed,0xbffbbf44,0xbf8ebf44,0xbec8bfed,
0x3f8e3fb5,0x3ec8bfb5,0xbfd5bfb5,0x3ffb3fb5,0x3ec83f44,0x3fd53fed,0xbffbbfed,0xbf8e3f44,0x3ff53f80,0x3f713f80,0xbf15bf80,0xbfe2bf80,
0x3fa23fd5,0xbfffbf8e,0xbfc6bf8e,0x3e49bfd5,0x3e493f44,0x3fa2bf44,0xbfffbfed,0x3fc63fed,0xbf71bec8,0x3f153ffb,0xbfe2bffb,0xbff5bec8,
0x3fed3f80,0x3f443f80,0xbf443f80,0xbfed3f80,0x3f443fb5,0xbfedbfb5,0xbfedbfb5,0x3f44bfb5,0xbf440000,0x3fed0000,0xbfedc000,0x3f444000,
0xbfedbfb5,0xbf443fb5,0xbf44bfb5,0xbfedbfb5,0x3fe23f80,0x3f153f80,0xbf71bf80,0xbff5bf80,0x3e493f8e,0xbfc6bfd5,0xbfffbfd5,0x3fa2bf8e,
0xbfc6bf44,0x3fff3f44,0xbfa2bfed,0xbe493fed,0xbff5bffb,0xbfe23ec8,0x3f15bec8,0xbf71bffb,0x3fd53f80,0x3ec83f80,0xbf8e3f80,0xbffb3f80,
0xbec83f44,0xbf8ebfed,0xbffbbfed,0x3fd5bf44,0xbffbbfb5,0x3fd53fb5,0xbec8bfb5,0xbf8e3fb5,0xbf8ebfed,0xbffbbf44,0x3fd53f44,0x3ec8bfed,
0x3fc63f80,0x3e493f80,0xbfa2bf80,0xbfffbf80,0xbf713ec8,0xbf15bffb,0xbfe2bffb,0x3ff5bec8,0xbff5bfed,0x3f713fed,0x3f15bf44,0xbfe23f44,
0x3e49bf8e,0xbfa2bfd5,0x3fff3fd5,0x3fc6bf8e,0x3f80,0xbfb53f80,0xc0003f80,0xbfb53f80,0xc000,0x3fb50000,0x40000000,0xbfb54000,
0x4000,0x3fb5c000,0xc0000000,0x3fb50000,0xc000,0xbfb50000,0x40000000,0x3fb5c000,0xbe493f80,0xbfc63f80,0xbfffbf80,0xbfa2bf80,
0x3f15bffb,0x3f713ec8,0x3ff53ec8,0xbfe23ffb,0xbf713fed,0x3ff5bfed,0xbfe2bf44,0x3f153f44,0x3fa2bfd5,0xbe49bf8e,0x3fc63f8e,0x3fffbfd5,
0xbec83f80,0xbfd53f80,0xbffb3f80,0xbf8e3f80,0x3f8ebfed,0x3ec83f44,0x3fd53f44,0xbffb3fed,0xbfd53fb5,0x3ffbbfb5,0xbf8ebfb5,0xbec83fb5,
0x3ffbbf44,0x3f8ebfed,0x3ec83fed,0x3fd5bf44,0xbf153f80,0xbfe23f80,0xbff5bf80,0xbf71bf80,0x3fc6bfd5,0xbe493f8e,0x3fa23f8e,0xbfff3fd5,
0xbfff3f44,0x3fc6bf44,0xbe49bfed,0xbfa23fed,0x3fe23ec8,0x3ff5bffb,0xbf713ffb,0x3f153ec8,0xbf443f80,0xbfed3f80,0xbfed3f80,0xbf443f80,
0x3fedbfb5,0xbf443fb5,0x3f443fb5,0xbfed3fb5,0xbfed0000,0x3f440000,0x3f44c000,0xbfed4000,0x3f443fb5,0x3fedbfb5,0xbfed3fb5,0xbf443fb5,
0xbf713f80,0xbff53f80,0xbfe2bf80,0xbf15bf80,0x3fffbf8e,0xbfa23fd5,0x3e493fd5,0xbfc63f8e,0xbfa2bf44,0xbe493f44,0x3fc6bfed,0xbfff3fed,
0xbf153ffb,0x3f71bec8,0xbff53ec8,0xbfe23ffb,0xbf8e3f80,0xbffb3f80,0xbfd53f80,0xbec83f80,0x3ffbbf44,0xbfd53fed,0xbec83fed,0xbf8e3f44,
0xbec8bfb5,0xbf8e3fb5,0x3ffbbfb5,0xbfd53fb5,0xbfd53fed,0xbec83f44,0xbf8ebf44,0xbffb3fed,0xbfa23f80,0xbfff3f80,0xbfc6bf80,0xbe49bf80,
0x3fe2bec8,0xbff53ffb,0xbf713ffb,0xbf153ec8,0x3f15bfed,0xbfe23fed,0x3ff5bf44,0xbf713f44,0xbfff3f8e,0xbfc63fd5,0x3e49bfd5,0xbfa23f8e,
0xc0003f80,0xbfb53f80,0x3f80,0x3fb53f80,0xc0004000,0x3fb50000,0x0,0x3fb5c000,0xc0004000,0x3fb5c000,0x0,0xbfb50000,
0xc0004000,0xbfb50000,0x0,0xbfb54000,0xbfff3f80,0xbfa23f80,0x3e49bf80,0x3fc6bf80,0xbff53ffb,0x3fe2bec8,0x3f15bec8,0x3f71bffb,
0xbfe23fed,0x3f15bfed,0x3f71bf44,0xbff53f44,0xbfc63fd5,0xbfff3f8e,0x3fa2bf8e,0xbe493fd5,0xbffb3f80,0xbf8e3f80,0x3ec83f80,0x3fd53f80,
0xbfd53fed,0x3ffbbf44,0x3f8ebf44,0x3ec8bfed,0xbf8e3fb5,0xbec8bfb5,0x3fd5bfb5,0xbffb3fb5,0xbec83f44,0xbfd53fed,0x3ffbbfed,0x3f8e3f44,
0xbff53f80,0xbf713f80,0x3f15bf80,0x3fe2bf80,0xbfa23fd5,0x3fffbf8e,0x3fc6bf8e,0xbe49bfd5,0xbe493f44,0xbfa2bf44,0x3fffbfed,0xbfc63fed,
0x3f71bec8,0xbf153ffb,0x3fe2bffb,0x3ff5bec8,0xbfed3f80,0xbf443f80,0x3f443f80,0x3fed3f80,0xbf443fb5,0x3fedbfb5,0x3fedbfb5,0xbf44bfb5,
0x3f440000,0xbfed0000,0x3fedc000,0xbf444000,0x3fedbfb5,0x3f443fb5,0x3f44bfb5,0x3fedbfb5,0xbfe23f80,0xbf153f80,0x3f71bf80,0x3ff5bf80,
0xbe493f8e,0x3fc6bfd5,0x3fffbfd5,0xbfa2bf8e,0x3fc6bf44,0xbfff3f44,0x3fa2bfed,0x3e493fed,0x3ff5bffb,0x3fe23ec8,0xbf15bec8,0x3f71bffb,
0xbfd53f80,0xbec83f80,0x3f8e3f80,0x3ffb3f80,0x3ec83f44,0x3f8ebfed,0x3ffbbfed,0xbfd5bf44,0x3ffbbfb5,0xbfd53fb5,0x3ec8bfb5,0x3f8e3fb5,
0x3f8ebfed,0x3ffbbf44,0xbfd53f44,0xbec8bfed,0xbfc63f80,0xbe493f80,0x3fa2bf80,0x3fffbf80,0x3f713ec8,0x3f15bffb,0x3fe2bffb,0xbff5bec8,
0x3ff5bfed,0xbf713fed,0xbf15bf44,0x3fe23f44,0xbe49bf8e,0x3fa2bfd5,0xbfff3fd5,0xbfc6bf8e,0x3f80,0x3fb53f80,0x40003f80,0x3fb53f80,
0xc000,0xbfb50000,0xc0000000,0x3fb54000,0x4000,0xbfb5c000,0x40000000,0xbfb50000,0xc000,0x3fb50000,0xc0000000,0xbfb5c000,
0x3e493f80,0x3fc63f80,0x3fffbf80,0x3fa2bf80,0xbf15bffb,0xbf713ec8,0xbff53ec8,0x3fe23ffb,0x3f713fed,0xbff5bfed,0x3fe2bf44,0xbf153f44,
0xbfa2bfd5,0x3e49bf8e,0xbfc63f8e,0xbfffbfd5,0x3ec83f80,0x3fd53f80,0x3ffb3f80,0x3f8e3f80,0xbf8ebfed,0xbec83f44,0xbfd53f44,0x3ffb3fed,
0x3fd53fb5,0xbffbbfb5,0x3f8ebfb5,0x3ec83fb5,0xbffbbf44,0xbf8ebfed,0xbec83fed,0xbfd5bf44,0x3f153f80,0x3fe23f80,0x3ff5bf80,0x3f71bf80,
0xbfc6bfd5,0x3e493f8e,0xbfa23f8e,0x3fff3fd5,0x3fff3f44,0xbfc6bf44,0x3e49bfed,0x3fa23fed,0xbfe23ec8,0xbff5bffb,0x3f713ffb,0xbf153ec8,
0x3f443f80,0x3fed3f80,0x3fed3f80,0x3f443f80,0xbfedbfb5,0x3f443fb5,0xbf443fb5,0x3fed3fb5,0x3fed0000,0xbf440000,0xbf44c000,0x3fed4000,
0xbf443fb5,0xbfedbfb5,0x3fed3fb5,0x3f443fb5,0x3f713f80,0x3ff53f80,0x3fe2bf80,0x3f15bf80,0xbfffbf8e,0x3fa23fd5,0xbe493fd5,0x3fc63f8e,
0x3fa2bf44,0x3e493f44,0xbfc6bfed,0x3fff3fed,0x3f153ffb,0xbf71bec8,0x3ff53ec8,0x3fe23ffb,0x3f8e3f80,0x3ffb3f80,0x3fd53f80,0x3ec83f80,
0xbffbbf44,0x3fd53fed,0x3ec83fed,0x3f8e3f44,0x3ec8bfb5,0x3f8e3fb5,0xbffbbfb5,0x3fd53fb5,0x3fd53fed,0x3ec83f44,0x3f8ebf44,0x3ffb3fed,
0x3fa23f80,0x3fff3f80,0x3fc6bf80,0x3e49bf80,0xbfe2bec8,0x3ff53ffb,0x3f713ffb,0x3f153ec8,0xbf15bfed,0x3fe23fed,0xbff5bf44,0x3f713f44,
0x3fff3f8e,0x3fc63fd5,0xbe49bfd5,0x3fa23f8e,0x40004000,0x3fb54000,0x0,0xbfb50000,0x40004000,0xbfb50000,0x0,0xbfb5c000,
0x40004000,0xbfb5c000,0x0,0x3fb50000,0x40004000,0x3fb50000,0x0,0x3fb54000,0x3fa23fb5,0xbe493fb5,0xbfc6bfb5,0xbfffbfb5,
0x3f713f8e,0xbff5bfd5,0xbfe2bfd5,0x3f15bf8e,0x3f153f44,0x3f71bf44,0xbff5bfed,0x3fe23fed,0x3e493ec8,0x3fc63ffb,0xbfffbffb,0xbfa23ec8,
0xbec80000,0xbfd50000,0xbffbc000,0xbf8ec000,0xbf8ebf44,0xbec8bfed,0xbfd5bfed,0x3ffb3f44,0xbfd5bfb5,0x3ffb3fb5,0xbf8ebfb5,0xbec83fb5,
0xbffbbfed,0xbf8e3f44,0xbec8bf44,0xbfd5bfed,0xbfe2bfb5,0xbff5bfb5,0xbf71bfb5,0x3f15bfb5,0xbfffbffb,0x3fc6bec8,0x3e49bec8,0x3fa23ffb,
0xbfc6bfed,0x3e493fed,0x3fa23f44,0xbfffbf44,0xbf15bf8e,0xbfe2bfd5,0x3ff53fd5,0x3f71bf8e,0xbfedc000,0xbf44c000,0x3f440000,0x3fed0000,
0xbf44bfb5,0x3fed3fb5,0x3fed3fb5,0xbf443fb5,0x3f440000,0xbfed0000,0x3fed4000,0xbf44c000,0x3fed3fb5,0x3f44bfb5,0x3f443fb5,0x3fed3fb5,
0xbf15bfb5,0x3f71bfb5,0x3ff53fb5,0x3fe23fb5,0x3fa23ec8,0x3e493ffb,0x3fc63ffb,0xbfffbec8,0x3fff3fed,0xbfa2bfed,0xbe493f44,0x3fc6bf44,
0x3f713fd5,0x3ff53f8e,0xbfe2bf8e,0xbf153fd5,0x3f8e0000,0x3ffb0000,0x3fd54000,0x3ec84000,0x3ffb3fed,0xbfd53f44,0xbec83f44,0xbf8ebfed,
0x3ec83fb5,0x3f8ebfb5,0xbffbbfb5,0x3fd53fb5,0xbfd5bf44,0xbec83fed,0xbf8ebfed,0xbffbbf44,0x3fff3fb5,0x3fc63fb5,0x3e493fb5,0xbfa23fb5,
0x3f153fd5,0xbfe2bf8e,0xbff5bf8e,0x3f71bfd5,0xbfe2bf44,0x3ff53f44,0xbf71bfed,0xbf153fed,0xbfa2bffb,0xbfffbec8,0x3fc63ec8,0x3e49bffb,
0x4000,0xbfb54000,0xc0000000,0xbfb50000,0xc000,0x3fb50000,0x40000000,0xbfb54000,0x4000,0x3fb5c000,0xc0000000,0x3fb50000,
0xc000,0xbfb50000,0x40000000,0x3fb5c000,0xbfc63fb5,0xbfff3fb5,0xbfa2bfb5,0x3e49bfb5,0x3fe2bf8e,0xbf153fd5,0x3f713fd5,0xbff53f8e,
0xbff53f44,0x3fe2bf44,0xbf15bfed,0xbf713fed,0x3fffbec8,0x3fa2bffb,0x3e493ffb,0x3fc6bec8,0xbffb0000,0xbf8e0000,0x3ec8c000,0x3fd5c000,
0x3fd53f44,0xbffb3fed,0xbf8e3fed,0xbec8bf44,0xbf8ebfb5,0xbec83fb5,0x3fd5bfb5,0xbffb3fb5,0x3ec83fed,0x3fd5bf44,0xbffb3f44,0xbf8e3fed,
0xbf71bfb5,0x3f15bfb5,0x3fe2bfb5,0x3ff5bfb5,0xbe493ffb,0xbfa23ec8,0xbfff3ec8,0x3fc6bffb,0x3fa2bfed,0xbfff3fed,0x3fc63f44,0xbe49bf44,
0xbff53f8e,0xbf713fd5,0xbf15bfd5,0xbfe23f8e,0x3f44c000,0x3fedc000,0x3fed0000,0x3f440000,0xbfed3fb5,0x3f44bfb5,0xbf44bfb5,0x3fedbfb5,
0x3fed0000,0xbf440000,0xbf444000,0x3fedc000,0xbf44bfb5,0xbfed3fb5,0x3fedbfb5,0x3f44bfb5,0x3ff5bfb5,0x3fe2bfb5,0x3f153fb5,0xbf713fb5,
0xbfc6bec8,0x3fffbffb,0x3fa2bffb,0x3e493ec8,0xbe493fed,0x3fc6bfed,0xbfff3f44,0x3fa2bf44,0x3fe2bfd5,0x3f15bf8e,0x3f713f8e,0x3ff5bfd5,
0x3fd50000,0x3ec80000,0xbf8e4000,0xbffb4000,0x3ec8bfed,0x3f8ebf44,0x3ffbbf44,0xbfd53fed,0xbffb3fb5,0x3fd5bfb5,0xbec8bfb5,0xbf8e3fb5,
0x3f8e3f44,0x3ffbbfed,0xbfd53fed,0xbec83f44,0x3e493fb5,0xbfa23fb5,0xbfff3fb5,0xbfc63fb5,0x3ff5bfd5,0xbf713f8e,0x3f153f8e,0xbfe23fd5,
0xbf71bf44,0xbf153f44,0x3fe2bfed,0xbff53fed,0xbfc63ffb,0xbe493ec8,0xbfa2bec8,0xbfff3ffb,0xc0004000,0xbfb54000,0x0,0x3fb50000,
0xc0004000,0x3fb50000,0x0,0x3fb5c000,0xc0004000,0x3fb5c000,0x0,0xbfb50000,0xc0004000,0xbfb50000,0x0,0xbfb54000,
0xbfa23fb5,0x3e493fb5,0x3fc6bfb5,0x3fffbfb5,0xbf713f8e,0x3ff5bfd5,0x3fe2bfd5,0xbf15bf8e,0xbf153f44,0xbf71bf44,0x3ff5bfed,0xbfe23fed,
0xbe493ec8,0xbfc63ffb,0x3fffbffb,0x3fa23ec8,0x3ec80000,0x3fd50000,0x3ffbc000,0x3f8ec000,0x3f8ebf44,0x3ec8bfed,0x3fd5bfed,0xbffb3f44,
0x3fd5bfb5,0xbffb3fb5,0x3f8ebfb5,0x3ec83fb5,0x3ffbbfed,0x3f8e3f44,0x3ec8bf44,0x3fd5bfed,0x3fe2bfb5,0x3ff5bfb5,0x3f71bfb5,0xbf15bfb5,
0x3fffbffb,0xbfc6bec8,0xbe49bec8,0xbfa23ffb,0x3fc6bfed,0xbe493fed,0xbfa23f44,0x3fffbf44,0x3f15bf8e,0x3fe2bfd5,0xbff53fd5,0xbf71bf8e,
0x3fedc000,0x3f44c000,0xbf440000,0xbfed0000,0x3f44bfb5,0xbfed3fb5,0xbfed3fb5,0x3f443fb5,0xbf440000,0x3fed0000,0xbfed4000,0x3f44c000,
0xbfed3fb5,0xbf44bfb5,0xbf443fb5,0xbfed3fb5,0x3f15bfb5,0xbf71bfb5,0xbff53fb5,0xbfe23fb5,0xbfa23ec8,0xbe493ffb,0xbfc63ffb,0x3fffbec8,
0xbfff3fed,0x3fa2bfed,0x3e493f44,0xbfc6bf44,0xbf713fd5,0xbff53f8e,0x3fe2bf8e,0x3f153fd5,0xbf8e0000,0xbffb0000,0xbfd54000,0xbec84000,
0xbffb3fed,0x3fd53f44,0x3ec83f44,0x3f8ebfed,0xbec83fb5,0xbf8ebfb5,0x3ffbbfb5,0xbfd53fb5,0x3fd5bf44,0x3ec83fed,0x3f8ebfed,0x3ffbbf44,
0xbfff3fb5,0xbfc63fb5,0xbe493fb5,0x3fa23fb5,0xbf153fd5,0x3fe2bf8e,0x3ff5bf8e,0xbf71bfd5,0x3fe2bf44,0xbff53f44,0x3f71bfed,0x3f153fed,
0x3fa2bffb,0x3fffbec8,0xbfc63ec8,0xbe49bffb,0x4000,0x3fb54000,0x40000000,0x3fb50000,0xc000,0xbfb50000,0xc0000000,0x3fb54000,
0x4000,0xbfb5c000,0x40000000,0xbfb50000,0xc000,0x3fb50000,0xc0000000,0xbfb5c000,0x3fc63fb5,0x3fff3fb5,0x3fa2bfb5,0xbe49bfb5,
0xbfe2bf8e,0x3f153fd5,0xbf713fd5,0x3ff53f8e,0x3ff53f44,0xbfe2bf44,0x3f15bfed,0x3f713fed,0xbfffbec8,0xbfa2bffb,0xbe493ffb,0xbfc6bec8,
0x3ffb0000,0x3f8e0000,0xbec8c000,0xbfd5c000,0xbfd53f44,0x3ffb3fed,0x3f8e3fed,0x3ec8bf44,0x3f8ebfb5,0x3ec83fb5,0xbfd5bfb5,0x3ffb3fb5,
0xbec83fed,0xbfd5bf44,0x3ffb3f44,0x3f8e3fed,0x3f71bfb5,0xbf15bfb5,0xbfe2bfb5,0xbff5bfb5,0x3e493ffb,0x3fa23ec8,0x3fff3ec8,0xbfc6bffb,
0xbfa2bfed,0x3fff3fed,0xbfc63f44,0x3e49bf44,0x3ff53f8e,0x3f713fd5,0x3f15bfd5,0x3fe23f8e,0xbf44c000,0xbfedc000,0xbfed0000,0xbf440000,
0x3fed3fb5,0xbf44bfb5,0x3f44bfb5,0xbfedbfb5,0xbfed0000,0x3f440000,0x3f444000,0xbfedc000,0x3f44bfb5,0x3fed3fb5,0xbfedbfb5,0xbf44bfb5,
0xbff5bfb5,0xbfe2bfb5,0xbf153fb5,0x3f713fb5,0x3fc6bec8,0xbfffbffb,0xbfa2bffb,0xbe493ec8,0x3e493fed,0xbfc6bfed,0x3fff3f44,0xbfa2bf44,
0xbfe2bfd5,0xbf15bf8e,0xbf713f8e,0xbff5bfd5,0xbfd50000,0xbec80000,0x3f8e4000,0x3ffb4000,0xbec8bfed,0xbf8ebf44,0xbffbbf44,0x3fd53fed,
0x3ffb3fb5,0xbfd5bfb5,0x3ec8bfb5,0x3f8e3fb5,0xbf8e3f44,0xbffbbfed,0x3fd53fed,0x3ec83f44,0xbe493fb5,0x3fa23fb5,0x3fff3fb5,0x3fc63fb5,
0xbff5bfd5,0x3f713f8e,0xbf153f8e,0x3fe23fd5,0x3f71bf44,0x3f153f44,0xbfe2bfed,0x3ff53fed,0x3fc63ffb,0x3e493ec8,0x3fa2bec8,0x3fff3ffb,
0x40004000,0x3fb54000,0x0,0xbfb50000,0x40004000,0xbfb50000,0x0,0xbfb5c000,0x40004000,0xbfb5c000,0x0,0x3fb50000,
0x40004000,0x3fb50000,0x0,0x3fb54000,0xbe490000,0xbfc60000,0xbfffc000,0xbfa2c000,0xbf15bec8,0xbf71bffb,0xbff5bffb,0x3fe23ec8,
0xbf71bf44,0x3ff53f44,0xbfe2bfed,0x3f153fed,0xbfa2bf8e,0x3e493fd5,0xbfc6bfd5,0xbfffbf8e,0xbffbc000,0xbf8ec000,0x3ec80000,0x3fd50000,
0xbfd5bfed,0x3ffb3f44,0x3f8e3f44,0x3ec83fed,0xbf8ebfb5,0xbec83fb5,0x3fd53fb5,0xbffbbfb5,0xbec8bf44,0xbfd5bfed,0x3ffb3fed,0x3f8ebf44,
0x3f150000,0x3fe20000,0x3ff54000,0x3f714000,0x3fc63f8e,0xbe493fd5,0x3fa23fd5,0xbfffbf8e,0x3fff3fed,0xbfc6bfed,0x3e493f44,0x3fa2bf44,
0x3fe23ffb,0x3ff53ec8,0xbf71bec8,0x3f153ffb,0x3fed4000,0x3f444000,0xbf440000,0xbfed0000,0x3f443fb5,0xbfedbfb5,0xbfedbfb5,0x3f44bfb5,
0xbf440000,0x3fed0000,0xbfedc000,0x3f444000,0xbfedbfb5,0xbf443fb5,0xbf44bfb5,0xbfedbfb5,0xbf710000,0xbff50000,0xbfe2c000,0xbf15c000,
0xbfffbfd5,0x3fa2bf8e,0xbe49bf8e,0x3fc63fd5,0xbfa2bfed,0xbe493fed,0x3fc63f44,0xbfffbf44,0x3f15bec8,0xbf71bffb,0x3ff53ffb,0x3fe2bec8,
0xbfd5c000,0xbec8c000,0x3f8e0000,0x3ffb0000,0x3ec8bf44,0x3f8e3fed,0x3ffb3fed,0xbfd53f44,0x3ffb3fb5,0xbfd5bfb5,0x3ec83fb5,0x3f8ebfb5,
0x3f8e3fed,0x3ffb3f44,0xbfd5bf44,0xbec83fed,0x3fa20000,0x3fff0000,0x3fc64000,0x3e494000,0x3fe23ffb,0xbff53ec8,0xbf713ec8,0xbf15bffb,
0xbf153f44,0x3fe2bf44,0xbff5bfed,0x3f713fed,0xbfffbfd5,0xbfc63f8e,0x3e49bf8e,0xbfa2bfd5,0x4000,0xbfb54000,0xc0000000,0xbfb50000,
0xc000,0x3fb50000,0x40000000,0xbfb54000,0x4000,0x3fb5c000,0xc0000000,0x3fb50000,0xc000,0xbfb50000,0x40000000,0x3fb5c000,
0xbfff0000,0xbfa20000,0x3e49c000,0x3fc6c000,0x3ff53ec8,0xbfe23ffb,0xbf153ffb,0xbf71bec8,0xbfe2bf44,0x3f153f44,0x3f71bfed,0xbff53fed,
0x3fc63f8e,0x3fffbfd5,0xbfa23fd5,0x3e493f8e,0x3ec8c000,0x3fd5c000,0x3ffb0000,0x3f8e0000,0xbf8e3fed,0xbec8bf44,0xbfd5bf44,0x3ffbbfed,
0x3fd5bfb5,0xbffb3fb5,0x3f8e3fb5,0x3ec8bfb5,0xbffb3f44,0xbf8e3fed,0xbec8bfed,0xbfd53f44,0x3ff50000,0x3f710000,0xbf154000,0xbfe24000,
0xbfa2bf8e,0x3fffbfd5,0x3fc6bfd5,0xbe493f8e,0x3e493fed,0x3fa2bfed,0xbfff3f44,0x3fc6bf44,0x3f71bffb,0xbf15bec8,0x3fe23ec8,0x3ff5bffb,
0xbf444000,0xbfed4000,0xbfed0000,0xbf440000,0x3fedbfb5,0xbf443fb5,0x3f443fb5,0xbfed3fb5,0xbfed0000,0x3f440000,0x3f44c000,0xbfed4000,
0x3f443fb5,0x3fedbfb5,0xbfed3fb5,0xbf443fb5,0xbfe20000,0xbf150000,0x3f71c000,0x3ff5c000,0x3e493fd5,0xbfc63f8e,0xbfff3f8e,0x3fa2bfd5,
0x3fc6bfed,0xbfff3fed,0x3fa23f44,0x3e49bf44,0xbff53ec8,0xbfe23ffb,0x3f15bffb,0xbf713ec8,0x3f8ec000,0x3ffbc000,0x3fd50000,0x3ec80000,
0xbffb3f44,0x3fd5bfed,0x3ec8bfed,0x3f8ebf44,0x3ec83fb5,0x3f8ebfb5,0xbffb3fb5,0x3fd5bfb5,0x3fd5bfed,0x3ec8bf44,0x3f8e3f44,0x3ffbbfed,
0x3fc60000,0x3e490000,0xbfa24000,0xbfff4000,0x3f71bffb,0x3f15bec8,0x3fe2bec8,0xbff53ffb,0xbff53f44,0x3f71bf44,0x3f15bfed,0xbfe23fed,
0xbe493fd5,0x3fa2bf8e,0xbfff3f8e,0xbfc63fd5,0xc0004000,0xbfb54000,0x0,0x3fb50000,0xc0004000,0x3fb50000,0x0,0x3fb5c000,
0xc0004000,0x3fb5c000,0x0,0xbfb50000,0xc0004000,0xbfb50000,0x0,0xbfb54000,0x3e490000,0x3fc60000,0x3fffc000,0x3fa2c000,
0x3f15bec8,0x3f71bffb,0x3ff5bffb,0xbfe23ec8,0x3f71bf44,0xbff53f44,0x3fe2bfed,0xbf153fed,0x3fa2bf8e,0xbe493fd5,0x3fc6bfd5,0x3fffbf8e,
0x3ffbc000,0x3f8ec000,0xbec80000,0xbfd50000,0x3fd5bfed,0xbffb3f44,0xbf8e3f44,0xbec83fed,0x3f8ebfb5,0x3ec83fb5,0xbfd53fb5,0x3ffbbfb5,
0x3ec8bf44,0x3fd5bfed,0xbffb3fed,0xbf8ebf44,0xbf150000,0xbfe20000,0xbff54000,0xbf714000,0xbfc63f8e,0x3e493fd5,0xbfa23fd5,0x3fffbf8e,
0xbfff3fed,0x3fc6bfed,0xbe493f44,0xbfa2bf44,0xbfe23ffb,0xbff53ec8,0x3f71bec8,0xbf153ffb,0xbfed4000,0xbf444000,0x3f440000,0x3fed0000,
0xbf443fb5,0x3fedbfb5,0x3fedbfb5,0xbf44bfb5,0x3f440000,0xbfed0000,0x3fedc000,0xbf444000,0x3fedbfb5,0x3f443fb5,0x3f44bfb5,0x3fedbfb5,
0x3f710000,0x3ff50000,0x3fe2c000,0x3f15c000,0x3fffbfd5,0xbfa2bf8e,0x3e49bf8e,0xbfc63fd5,0x3fa2bfed,0x3e493fed,0xbfc63f44,0x3fffbf44,
0xbf15bec8,0x3f71bffb,0xbff53ffb,0xbfe2bec8,0x3fd5c000,0x3ec8c000,0xbf8e0000,0xbffb0000,0xbec8bf44,0xbf8e3fed,0xbffb3fed,0x3fd53f44,
0xbffb3fb5,0x3fd5bfb5,0xbec83fb5,0xbf8ebfb5,0xbf8e3fed,0xbffb3f44,0x3fd5bf44,0x3ec83fed,0xbfa20000,0xbfff0000,0xbfc64000,0xbe494000,
0xbfe23ffb,0x3ff53ec8,0x3f713ec8,0x3f15bffb,0x3f153f44,0xbfe2bf44,0x3ff5bfed,0xbf713fed,0x3fffbfd5,0x3fc63f8e,0xbe49bf8e,0x3fa2bfd5,
0x4000,0x3fb54000,0x40000000,0x3fb50000,0xc000,0xbfb50000,0xc0000000,0x3fb54000,0x4000,0xbfb5c000,0x40000000,0xbfb50000,
0xc000,0x3fb50000,0xc0000000,0xbfb5c000,0x3fff0000,0x3fa20000,0xbe49c000,0xbfc6c000,0xbff53ec8,0x3fe23ffb,0x3f153ffb,0x3f71bec8,
0x3fe2bf44,0xbf153f44,0xbf71bfed,0x3ff53fed,0xbfc63f8e,0xbfffbfd5,0x3fa23fd5,0xbe493f8e,0xbec8c000,0xbfd5c000,0xbffb0000,0xbf8e0000,
0x3f8e3fed,0x3ec8bf44,0x3fd5bf44,0xbffbbfed,0xbfd5bfb5,0x3ffb3fb5,0xbf8e3fb5,0xbec8bfb5,0x3ffb3f44,0x3f8e3fed,0x3ec8bfed,0x3fd53f44,
0xbff50000,0xbf710000,0x3f154000,0x3fe24000,0x3fa2bf8e,0xbfffbfd5,0xbfc6bfd5,0x3e493f8e,0xbe493fed,0xbfa2bfed,0x3fff3f44,0xbfc6bf44,
0xbf71bffb,0x3f15bec8,0xbfe23ec8,0xbff5bffb,0x3f444000,0x3fed4000,0x3fed0000,0x3f440000,0xbfedbfb5,0x3f443fb5,0xbf443fb5,0x3fed3fb5,
0x3fed0000,0xbf440000,0xbf44c000,0x3fed4000,0xbf443fb5,0xbfedbfb5,0x3fed3fb5,0x3f443fb5,0x3fe20000,0x3f150000,0xbf71c000,0xbff5c000,
0xbe493fd5,0x3fc63f8e,0x3fff3f8e,0xbfa2bfd5,0xbfc6bfed,0x3fff3fed,0xbfa23f44,0xbe49bf44,0x3ff53ec8,0x3fe23ffb,0xbf15bffb,0x3f713ec8,
0xbf8ec000,0xbffbc000,0xbfd50000,0xbec80000,0x3ffb3f44,0xbfd5bfed,0xbec8bfed,0xbf8ebf44,0xbec83fb5,0xbf8ebfb5,0x3ffb3fb5,0xbfd5bfb5,
0xbfd5bfed,0xbec8bf44,0xbf8e3f44,0xbffbbfed,0xbfc60000,0xbe490000,0x3fa24000,0x3fff4000,0xbf71bffb,0xbf15bec8,0xbfe2bec8,0x3ff53ffb,
0x3ff53f44,0xbf71bf44,0xbf15bfed,0x3fe23fed,0x3e493fd5,0xbfa2bf8e,0x3fff3f8e,0x3fc63fd5,0x40004000,0x3fb54000,0x0,0xbfb50000,
0x40004000,0xbfb50000,0x0,0xbfb5c000,0x40004000,0xbfb5c000,0x0,0x3fb50000,0x40004000,0x3fb50000,0x0,0x3fb54000,
0xbfc6bfb5,0xbfffbfb5,0xbfa2bfb5,0x3e49bfb5,0xbfe2bfd5,0x3f15bf8e,0xbf71bf8e,0x3ff53fd5,0xbff5bfed,0x3fe23fed,0xbf15bf44,0xbf713f44,
0xbfffbffb,0xbfa23ec8,0xbe49bec8,0xbfc6bffb,0x3ec80000,0x3fd50000,0x3ffb4000,0x3f8e4000,0x3f8e3f44,0x3ec83fed,0x3fd53fed,0xbffbbf44,
0x3fd53fb5,0xbffbbfb5,0x3f8e3fb5,0x3ec8bfb5,0x3ffb3fed,0x3f8ebf44,0x3ec83f44,0x3fd53fed,0x3f713fb5,0xbf153fb5,0xbfe2bfb5,0xbff5bfb5,
0xbe493ec8,0xbfa2bffb,0xbfffbffb,0x3fc6bec8,0xbfa2bf44,0x3fff3f44,0xbfc6bfed,0x3e493fed,0xbff5bfd5,0xbf713f8e,0xbf15bf8e,0xbfe2bfd5,
0xbfedc000,0xbf44c000,0x3f440000,0x3fed0000,0xbf44bfb5,0x3fed3fb5,0x3fed3fb5,0xbf443fb5,0x3f440000,0xbfed0000,0x3fed4000,0xbf44c000,
0x3fed3fb5,0x3f44bfb5,0x3f443fb5,0x3fed3fb5,0x3ff53fb5,0x3fe23fb5,0x3f153fb5,0xbf713fb5,0x3fc63ffb,0xbfffbec8,0xbfa2bec8,0xbe49bffb,
0xbe493f44,0x3fc6bf44,0xbfffbfed,0x3fa23fed,0xbfe2bf8e,0xbf153fd5,0xbf71bfd5,0xbff5bf8e,0xbf8e0000,0xbffb0000,0xbfd5c000,0xbec8c000,
0xbffbbfed,0x3fd5bf44,0x3ec8bf44,0x3f8e3fed,0xbec8bfb5,0xbf8e3fb5,0x3ffb3fb5,0xbfd5bfb5,0x3fd53f44,0x3ec8bfed,0x3f8e3fed,0x3ffb3f44,
0xbe49bfb5,0x3fa2bfb5,0x3fff3fb5,0x3fc63fb5,0x3ff53f8e,0xbf713fd5,0x3f153fd5,0xbfe2bf8e,0x3f713fed,0x3f15bfed,0xbfe2bf44,0x3ff53f44,
0xbfc6bec8,0xbe493ffb,0xbfa2bffb,0xbfffbec8,0x4000,0xbfb54000,0xc0000000,0xbfb50000,0xc000,0x3fb50000,0x40000000,0xbfb54000,
0x4000,0x3fb5c000,0xc0000000,0x3fb50000,0xc000,0xbfb50000,0x40000000,0x3fb5c000,0xbfa2bfb5,0x3e49bfb5,0x3fc6bfb5,0x3fffbfb5,
0x3f713fd5,0xbff53f8e,0xbfe23f8e,0x3f15bfd5,0xbf15bfed,0xbf713fed,0x3ff5bf44,0xbfe23f44,0x3e493ffb,0x3fc6bec8,0xbfff3ec8,0xbfa23ffb,
0x3ffb0000,0x3f8e0000,0xbec84000,0xbfd54000,0xbfd5bf44,0x3ffbbfed,0x3f8ebfed,0x3ec83f44,0x3f8e3fb5,0x3ec8bfb5,0xbfd53fb5,0x3ffbbfb5,
0xbec8bfed,0xbfd53f44,0x3ffbbf44,0x3f8ebfed,0xbfe23fb5,0xbff53fb5,0xbf71bfb5,0x3f15bfb5,0x3fffbec8,0xbfc63ffb,0xbe493ffb,0xbfa23ec8,
0xbfc6bf44,0x3e493f44,0x3fa2bfed,0xbfff3fed,0x3f153fd5,0x3fe2bf8e,0xbff53f8e,0xbf713fd5,0x3f44c000,0x3fedc000,0x3fed0000,0x3f440000,
0xbfed3fb5,0x3f44bfb5,0xbf44bfb5,0x3fedbfb5,0x3fed0000,0xbf440000,0xbf444000,0x3fedc000,0xbf44bfb5,0xbfed3fb5,0x3fedbfb5,0x3f44bfb5,
0x3f153fb5,0xbf713fb5,0xbff53fb5,0xbfe23fb5,0x3fa2bffb,0x3e493ec8,0x3fc63ec8,0xbfff3ffb,0xbfff3f44,0x3fa2bf44,0x3e49bfed,0xbfc63fed,
0x3f713f8e,0x3ff5bfd5,0xbfe23fd5,0xbf153f8e,0xbfd50000,0xbec80000,0x3f8ec000,0x3ffbc000,0xbec83fed,0xbf8e3f44,0xbffb3f44,0x3fd5bfed,
0x3ffbbfb5,0xbfd53fb5,0x3ec83fb5,0x3f8ebfb5,0xbf8ebf44,0xbffb3fed,0x3fd5bfed,0x3ec8bf44,0x3fffbfb5,0x3fc6bfb5,0x3e493fb5,0xbfa23fb5,
0xbf15bf8e,0x3fe2bfd5,0x3ff5bfd5,0xbf713f8e,0xbfe23fed,0x3ff5bfed,0xbf71bf44,0xbf153f44,0x3fa23ec8,0x3fffbffb,0xbfc63ffb,0xbe493ec8,
0xc0004000,0xbfb54000,0x0,0x3fb50000,0xc0004000,0x3fb50000,0x0,0x3fb5c000,0xc0004000,0x3fb5c000,0x0,0xbfb50000,
0xc0004000,0xbfb50000,0x0,0xbfb54000,0x3fc6bfb5,0x3fffbfb5,0x3fa2bfb5,0xbe49bfb5,0x3fe2bfd5,0xbf15bf8e,0x3f71bf8e,0xbff53fd5,
0x3ff5bfed,0xbfe23fed,0x3f15bf44,0x3f713f44,0x3fffbffb,0x3fa23ec8,0x3e49bec8,0x3fc6bffb,0xbec80000,0xbfd50000,0xbffb4000,0xbf8e4000,
0xbf8e3f44,0xbec83fed,0xbfd53fed,0x3ffbbf44,0xbfd53fb5,0x3ffbbfb5,0xbf8e3fb5,0xbec8bfb5,0xbffb3fed,0xbf8ebf44,0xbec83f44,0xbfd53fed,
0xbf713fb5,0x3f153fb5,0x3fe2bfb5,0x3ff5bfb5,0x3e493ec8,0x3fa2bffb,0x3fffbffb,0xbfc6bec8,0x3fa2bf44,0xbfff3f44,0x3fc6bfed,0xbe493fed,
0x3ff5bfd5,0x3f713f8e,0x3f15bf8e,0x3fe2bfd5,0x3fedc000,0x3f44c000,0xbf440000,0xbfed0000,0x3f44bfb5,0xbfed3fb5,0xbfed3fb5,0x3f443fb5,
0xbf440000,0x3fed0000,0xbfed4000,0x3f44c000,0xbfed3fb5,0xbf44bfb5,0xbf443fb5,0xbfed3fb5,0xbff53fb5,0xbfe23fb5,0xbf153fb5,0x3f713fb5,
0xbfc63ffb,0x3fffbec8,0x3fa2bec8,0x3e49bffb,0x3e493f44,0xbfc6bf44,0x3fffbfed,0xbfa23fed,0x3fe2bf8e,0x3f153fd5,0x3f71bfd5,0x3ff5bf8e,
0x3f8e0000,0x3ffb0000,0x3fd5c000,0x3ec8c000,0x3ffbbfed,0xbfd5bf44,0xbec8bf44,0xbf8e3fed,0x3ec8bfb5,0x3f8e3fb5,0xbffb3fb5,0x3fd5bfb5,
0xbfd53f44,0xbec8bfed,0xbf8e3fed,0xbffb3f44,0x3e49bfb5,0xbfa2bfb5,0xbfff3fb5,0xbfc63fb5,0xbff53f8e,0x3f713fd5,0xbf153fd5,0x3fe2bf8e,
0xbf713fed,0xbf15bfed,0x3fe2bf44,0xbff53f44,0x3fc6bec8,0x3e493ffb,0x3fa2bffb,0x3fffbec8,0x4000,0x3fb54000,0x40000000,0x3fb50000,
0xc000,0xbfb50000,0xc0000000,0x3fb54000,0x4000,0xbfb5c000,0x40000000,0xbfb50000,0xc000,0x3fb50000,0xc0000000,0xbfb5c000,
0x3fa2bfb5,0xbe49bfb5,0xbfc6bfb5,0xbfffbfb5,0xbf713fd5,0x3ff53f8e,0x3fe23f8e,0xbf15bfd5,0x3f15bfed,0x3f713fed,0xbff5bf44,0x3fe23f44,
0xbe493ffb,0xbfc6bec8,0x3fff3ec8,0x3fa23ffb,0xbffb0000,0xbf8e0000,0x3ec84000,0x3fd54000,0x3fd5bf44,0xbffbbfed,0xbf8ebfed,0xbec83f44,
0xbf8e3fb5,0xbec8bfb5,0x3fd53fb5,0xbffbbfb5,0x3ec8bfed,0x3fd53f44,0xbffbbf44,0xbf8ebfed,0x3fe23fb5,0x3ff53fb5,0x3f71bfb5,0xbf15bfb5,
0xbfffbec8,0x3fc63ffb,0x3e493ffb,0x3fa23ec8,0x3fc6bf44,0xbe493f44,0xbfa2bfed,0x3fff3fed,0xbf153fd5,0xbfe2bf8e,0x3ff53f8e,0x3f713fd5,
0xbf44c000,0xbfedc000,0xbfed0000,0xbf440000,0x3fed3fb5,0xbf44bfb5,0x3f44bfb5,0xbfedbfb5,0xbfed0000,0x3f440000,0x3f444000,0xbfedc000,
0x3f44bfb5,0x3fed3fb5,0xbfedbfb5,0xbf44bfb5,0xbf153fb5,0x3f713fb5,0x3ff53fb5,0x3fe23fb5,0xbfa2bffb,0xbe493ec8,0xbfc63ec8,0x3fff3ffb,
0x3fff3f44,0xbfa2bf44,0xbe49bfed,0x3fc63fed,0xbf713f8e,0xbff5bfd5,0x3fe23fd5,0x3f153f8e,0x3fd50000,0x3ec80000,0xbf8ec000,0xbffbc000,
0x3ec83fed,0x3f8e3f44,0x3ffb3f44,0xbfd5bfed,0xbffbbfb5,0x3fd53fb5,0xbec83fb5,0xbf8ebfb5,0x3f8ebf44,0x3ffb3fed,0xbfd5bfed,0xbec8bf44,
0xbfffbfb5,0xbfc6bfb5,0xbe493fb5,0x3fa23fb5,0x3f15bf8e,0xbfe2bfd5,0xbff5bfd5,0x3f713f8e,0x3fe23fed,0xbff5bfed,0x3f71bf44,0x3f153f44,
0xbfa23ec8,0xbfffbffb,0x3fc63ffb,0x3e493ec8,0x80003f80,0x3f800000,0x80003f80,0x3f800000,0x80003f80,0x3f800000,0x80003f80,0x3f800000,
0x80003f80,0x3f800000,0x80003f80,0x3f800000,0x80003f80,0x3f800000,0x80003f80,0x3f800000,0x80003f80,0x3f800000,0x8000bf80,0xbf800000,
0x3f353f35,0x3f35bf35,0xbf35bf35,0xbf353f35,0x3f800000,0xbf80,0xbf800000,0x3f80,0x3f35bf35,0xbf35bf35,0xbf353f35,0x3f353f35,
0x80003f80,0x3f800000,0x80003f80,0x3f800000,0x3f800000,0xbf80,0x3f800000,0xbf80,0x8000bf80,0xbf800000,0x8000bf80,0xbf800000,
0xbf800000,0x3f80,0xbf800000,0x3f80,0x80003f80,0x3f800000,0x8000bf80,0xbf800000,0x3f35bf35,0xbf35bf35,0xbf353f35,0x3f353f35,
0xbf800000,0x3f80,0x3f800000,0xbf80,0x3f353f35,0x3f35bf35,0xbf35bf35,0xbf353f35,0x80003f80,0x3f800000,0x80003f80,0x3f800000,
0x8000bf80,0xbf800000,0x8000bf80,0xbf800000,0x80003f80,0x3f800000,0x80003f80,0x3f800000,0x8000bf80,0xbf800000,0x8000bf80,0xbf800000,
0x80003f80,0x3f800000,0x8000bf80,0xbf800000,0xbf35bf35,0xbf353f35,0x3f353f35,0x3f35bf35,0x3f800000,0xbf80,0xbf800000,0x3f80,
0xbf353f35,0x3f353f35,0x3f35bf35,0xbf35bf35,0x80003f80,0x3f800000,0x80003f80,0x3f800000,0xbf800000,0x3f80,0xbf800000,0x3f80,
0x8000bf80,0xbf800000,0x8000bf80,0xbf800000,0x3f800000,0xbf80,0x3f800000,0xbf80,0x80003f80,0x3f800000,0x8000bf80,0xbf800000,
0xbf353f35,0x3f353f35,0x3f35bf35,0xbf35bf35,0xbf800000,0x3f80,0x3f800000,0xbf80,0xbf35bf35,0xbf353f35,0x3f353f35,0x3f35bf35,
0x3f803f80,0x80008000,0x80008000,0xbf80bf80,0x3f803f80,0x80008000,0x80008000,0xbf80bf80,0x3f803f80,0x80008000,0x80008000,0xbf80bf80,
0x3f803f80,0x80008000,0x80008000,0xbf80bf80,0x3f353f80,0x3f358000,0x3f358000,0xbf35bf80,0xbf350000,0x3f353f80,0x3f353f80,0x3f358000,
0xbf35bf80,0xbf358000,0xbf358000,0x3f353f80,0x3f350000,0xbf35bf80,0xbf35bf80,0xbf358000,0x3f80,0x3f808000,0x3f808000,0x8000bf80,
0xbf80,0xbf808000,0xbf808000,0x80003f80,0x3f80,0x3f808000,0x3f808000,0x8000bf80,0xbf80,0xbf808000,0xbf808000,0x80003f80,
0xbf353f80,0x3f358000,0x3f358000,0x3f35bf80,0x3f350000,0x3f35bf80,0x3f35bf80,0xbf358000,0x3f35bf80,0xbf358000,0xbf358000,0xbf353f80,
0xbf350000,0xbf353f80,0xbf353f80,0x3f358000,0xbf803f80,0x80008000,0x80008000,0x3f80bf80,0xbf803f80,0x80008000,0x80008000,0x3f80bf80,
0xbf803f80,0x80008000,0x80008000,0x3f80bf80,0xbf803f80,0x80008000,0x80008000,0x3f80bf80,0xbf353f80,0xbf358000,0xbf358000,0x3f35bf80,
0x3f350000,0xbf353f80,0xbf353f80,0xbf358000,0x3f35bf80,0x3f358000,0x3f358000,0xbf353f80,0xbf350000,0x3f35bf80,0x3f35bf80,0x3f358000,
0x3f80,0xbf808000,0xbf808000,0x8000bf80,0xbf80,0x3f808000,0x3f808000,0x80003f80,0x3f80,0xbf808000,0xbf808000,0x8000bf80,
0xbf80,0x3f808000,0x3f808000,0x80003f80,0x3f353f80,0xbf358000,0xbf358000,0xbf35bf80,0xbf350000,0xbf35bf80,0xbf35bf80,0x3f358000,
0xbf35bf80,0x3f358000,0x3f358000,0x3f353f80,0x3f350000,0x3f353f80,0x3f353f80,0xbf358000,0x3f800000,0x0,0x3f800000,0x0,
0x3f800000,0x0,0x3f800000,0x0,0x3f800000,0x0,0x3f800000,0x0,0x3f800000,0x0,0x3f800000,0x0,
0x3f800000,0x0,0x3f7fb10f,0xbd48fb30,0x3f7ec46d,0xbdc8bd36,0x3f7d3aac,0xbe164083,0x3f7b14be,0xbe47c5c2,0x3f7853f8,0xbe78cfcc,
0x3f74fa0b,0xbe94a031,0x3f710908,0xbeac7cd4,0x3f800000,0x0,0x3f7ec46d,0xbdc8bd36,0x3f7b14be,0xbe47c5c2,0x3f74fa0b,0xbe94a031,
0x3f6c835e,0xbec3ef15,0x3f61c598,0xbef15aea,0x3f54db31,0xbf0e39da,0x3f45e403,0xbf226799,0x3f800000,0x0,0x3f7d3aac,0xbe164083,
0x3f74fa0b,0xbe94a031,0x3f676bd8,0xbedae880,0x3f54db31,0xbf0e39da,0x3f3daef9,0xbf2beb4a,0x3f226799,0xbf45e403,0x3f039c3d,0xbf5b941a,
0x3f800000,0x0,0x3f7b14be,0xbe47c5c2,0x3f6c835e,0xbec3ef15,0x3f54db31,0xbf0e39da,0x3f3504f3,0xbf3504f3,0x3f0e39da,0xbf54db31,
0x3ec3ef15,0xbf6c835e,0x3e47c5c2,0xbf7b14be,0x3f800000,0x0,0x3f7853f8,0xbe78cfcc,0x3f61c598,0xbef15aea,0x3f3daef9,0xbf2beb4a,
0x3f0e39da,0xbf54db31,0x3eac7cd4,0xbf710908,0x3dc8bd36,0xbf7ec46d,0xbe164083,0xbf7d3aac,0x3f800000,0x0,0x3f74fa0b,0xbe94a031,
0x3f54db31,0xbf0e39da,0x3f226799,0xbf45e403,0x3ec3ef15,0xbf6c835e,0x3dc8bd36,0xbf7ec46d,0xbe47c5c2,0xbf7b14be,0xbef15aea,0xbf61c598,
0x3f800000,0x0,0x3f710908,0xbeac7cd4,0x3f45e403,0xbf226799,0x3f039c3d,0xbf5b941a,0x3e47c5c2,0xbf7b14be,0xbe164083,0xbf7d3aac,
0xbef15aea,0xbf61c598,0xbf3daef9,0xbf2beb4a,0x3f800000,0x0,0x3f800000,0x0,0x3f800000,0x0,0x3f800000,0x0,
0x3f800000,0x0,0x3f800000,0x0,0x3f800000,0x0,0x3f800000,0x0,0x3f6c835e,0xbec3ef15,0x3f676bd8,0xbedae880,
0x3f61c598,0xbef15aea,0x3f5b941a,0xbf039c3d,0x3f54db31,0xbf0e39da,0x3f4d9f02,0xbf187fc0,0x3f45e403,0xbf226799,0x3f3daef9,0xbf2beb4a,
0x3f3504f3,0xbf3504f3,0x3f226799,0xbf45e403,0x3f0e39da,0xbf54db31,0x3ef15aea,0xbf61c598,0x3ec3ef15,0xbf6c835e,0x3e94a031,0xbf74fa0b,
0x3e47c5c2,0xbf7b14be,0x3dc8bd36,0xbf7ec46d,0x3ec3ef15,0xbf6c835e,0x3e78cfcc,0xbf7853f8,0x3dc8bd36,0xbf7ec46d,0xbd48fb30,0xbf7fb10f,
0xbe47c5c2,0xbf7b14be,0xbeac7cd4,0xbf710908,0xbef15aea,0xbf61c598,0xbf187fc0,0xbf4d9f02,0x0,0xbf800000,0xbe47c5c2,0xbf7b14be,
0xbec3ef15,0xbf6c835e,0xbf0e39da,0xbf54db31,0xbf3504f3,0xbf3504f3,0xbf54db31,0xbf0e39da,0xbf6c835e,0xbec3ef15,0xbf7b14be,0xbe47c5c2,
0xbec3ef15,0xbf6c835e,0xbf187fc0,0xbf4d9f02,0xbf45e403,0xbf226799,0xbf676bd8,0xbedae880,0xbf7b14be,0xbe47c5c2,0xbf7fb10f,0x3d48fb30,
0xbf74fa0b,0x3e94a031,0xbf5b941a,0x3f039c3d,0xbf3504f3,0xbf3504f3,0xbf61c598,0xbef15aea,0xbf7b14be,0xbe47c5c2,0xbf7ec46d,0x3dc8bd36,
0xbf6c835e,0x3ec3ef15,0xbf45e403,0x3f226799,0xbf0e39da,0x3f54db31,0xbe94a031,0x3f74fa0b,0xbf6c835e,0xbec3ef15,0xbf7fb10f,0xbd48fb30,
0xbf74fa0b,0x3e94a031,0xbf4d9f02,0x3f187fc0,0xbf0e39da,0x3f54db31,0xbe78cfcc,0x3f7853f8,0x3dc8bd36,0x3f7ec46d,0x3edae880,0x3f676bd8,
0x80003f80,0x3f800000,0x3f800000,0xbf80,0x3ec43f6d,0x3f6dbec4,0x3f6dbec4,0xbec4bf6d,0x3f353f35,0x3f35bf35,0x3f35bf35,0xbf35bf35,
0x3f6d3ec4,0x3ec4bf6d,0x3ec4bf6d,0xbf6dbec4,0x80003f80,0x3f800000,0xbf800000,0x3f80,0x3f6d3ec4,0x3ec4bf6d,0xbec43f6d,0x3f6d3ec4,
0x3f35bf35,0xbf35bf35,0x3f353f35,0x3f35bf35,0xbec4bf6d,0xbf6d3ec4,0x3f6dbec4,0xbec4bf6d,0x80003f80,0x3f800000,0x3f800000,0xbf80,
0x3f6dbec4,0xbec4bf6d,0xbec4bf6d,0xbf6d3ec4,0xbf35bf35,0xbf353f35,0xbf353f35,0x3f353f35,0xbec43f6d,0x3f6d3ec4,0x3f6d3ec4,0x3ec4bf6d,
0x80003f80,0x3f800000,0xbf800000,0x3f80,0x3ec4bf6d,0xbf6dbec4,0x3f6d3ec4,0x3ec4bf6d,0xbf353f35,0x3f353f35,0xbf35bf35,0xbf353f35,
0x3f6dbec4,0xbec4bf6d,0x3ec43f6d,0x3f6dbec4,0x80003f80,0x3f800000,0x3f800000,0xbf80,0xbec4bf6d,0xbf6d3ec4,0xbf6d3ec4,0x3ec43f6d,
0x3f353f35,0x3f35bf35,0x3f35bf35,0xbf35bf35,0xbf6dbec4,0xbec43f6d,0xbec43f6d,0x3f6d3ec4,0x80003f80,0x3f800000,0xbf800000,0x3f80,
0xbf6dbec4,0xbec43f6d,0x3ec4bf6d,0xbf6dbec4,0x3f35bf35,0xbf35bf35,0x3f353f35,0x3f35bf35,0x3ec43f6d,0x3f6dbec4,0xbf6d3ec4,0x3ec43f6d,
0x80003f80,0x3f800000,0x3f800000,0xbf80,0xbf6d3ec4,0x3ec43f6d,0x3ec43f6d,0x3f6dbec4,0xbf35bf35,0xbf353f35,0xbf353f35,0x3f353f35,
0x3ec4bf6d,0xbf6dbec4,0xbf6dbec4,0xbec43f6d,0x80003f80,0x3f800000,0xbf800000,0x3f80,0xbec43f6d,0x3f6d3ec4,0xbf6dbec4,0xbec43f6d,
0xbf353f35,0x3f353f35,0xbf35bf35,0xbf353f35,0xbf6d3ec4,0x3ec43f6d,0xbec4bf6d,0xbf6d3ec4,0x3f803f80,0x80008000,0x80008000,0xbf80bf80,
0x3f803f80,0x80008000,0x80008000,0xbf80bf80,0x3f803f80,0x80008000,0x80008000,0xbf80bf80,0x3f803f80,0x80008000,0x80008000,0xbf80bf80,
0x3ec43f6d,0x3f6d3ec4,0x3f6d3ec4,0xbec4bf6d,0xbf6dbec4,0x3ec43f6d,0x3ec43f6d,0x3f6d3ec4,0xbec4bf6d,0xbf6dbec4,0xbf6dbec4,0x3ec43f6d,
0x3f6d3ec4,0xbec4bf6d,0xbec4bf6d,0xbf6dbec4,0xbf353f35,0x3f353f35,0x3f353f35,0x3f35bf35,0x3f35bf35,0xbf35bf35,0xbf35bf35,0xbf353f35,
0xbf353f35,0x3f353f35,0x3f353f35,0x3f35bf35,0x3f35bf35,0xbf35bf35,0xbf35bf35,0xbf353f35,0xbf6d3ec4,0xbec43f6d,0xbec43f6d,0x3f6dbec4,
0xbec43f6d,0x3f6dbec4,0x3f6dbec4,0x3ec4bf6d,0x3f6dbec4,0x3ec4bf6d,0x3ec4bf6d,0xbf6d3ec4,0x3ec4bf6d,0xbf6d3ec4,0xbf6d3ec4,0xbec43f6d,
0x0,0xbf803f80,0xbf803f80,0x80008000,0x0,0xbf803f80,0xbf803f80,0x80008000,0x0,0xbf803f80,0xbf803f80,0x80008000,
0x0,0xbf803f80,0xbf803f80,0x80008000,0x3f6dbec4,0xbec43f6d,0xbec43f6d,0xbf6d3ec4,0x3ec4bf6d,0x3f6dbec4,0x3f6dbec4,0xbec43f6d,
0xbf6d3ec4,0x3ec4bf6d,0x3ec4bf6d,0x3f6dbec4,0xbec43f6d,0xbf6d3ec4,0xbf6d3ec4,0x3ec4bf6d,0x3f35bf35,0x3f353f35,0x3f353f35,0xbf353f35,
0xbf353f35,0xbf35bf35,0xbf35bf35,0x3f35bf35,0x3f35bf35,0x3f353f35,0x3f353f35,0xbf353f35,0xbf353f35,0xbf35bf35,0xbf35bf35,0x3f35bf35,
0xbec4bf6d,0x3f6d3ec4,0x3f6d3ec4,0x3ec43f6d,0x3f6d3ec4,0x3ec43f6d,0x3ec43f6d,0xbf6dbec4,0x3ec43f6d,0xbf6dbec4,0xbf6dbec4,0xbec4bf6d,
0xbf6dbec4,0xbec4bf6d,0xbec4bf6d,0x3f6d3ec4,0x3f800000,0x0,0x3f7fec43,0xbcc90ab0,0x3f7fb10f,0xbd48fb30,0x3f7f4e6d,0xbd96a905,
0x3f7ec46d,0xbdc8bd36,0x3f7e1324,0xbdfab273,0x3f7d3aac,0xbe164083,0x3f7c3b28,0xbe2f10a2,0x3f800000,0x0,0x3f7f4e6d,0xbd96a905,
0x3f7d3aac,0xbe164083,0x3f79c79d,0xbe605c13,0x3f74fa0b,0xbe94a031,0x3f6ed89e,0xbeb8442a,0x3f676bd8,0xbedae880,0x3f5ebe05,0xbefc5d27,
0x3f800000,0x0,0x3f7e1324,0xbdfab273,0x3f7853f8,0xbe78cfcc,0x3f6ed89e,0xbeb8442a,0x3f61c598,0xbef15aea,0x3f514d3d,0xbf13682a,
0x3f3daef9,0xbf2beb4a,0x3f273656,0xbf41d870,0x3f800000,0x0,0x3f7c3b28,0xbe2f10a2,0x3f710908,0xbeac7cd4,0x3f5ebe05,0xbefc5d27,
0x3f45e403,0xbf226799,0x3f273656,0xbf41d870,0x3f039c3d,0xbf5b941a,0x3eb8442a,0xbf6ed89e,0x3f800000,0x0,0x3f79c79d,0xbe605c13,
0x3f676bd8,0xbedae880,0x3f49d112,0xbf1d7fd1,0x3f226799,0xbf45e403,0x3ee63375,0xbf64aa59,0x3e78cfcc,0xbf7853f8,0x3cc90ab0,0xbf7fec43,
0x3f800000,0x0,0x3f76ba07,0xbe888e93,0x3f5b941a,0xbf039c3d,0x3f3085bb,0xbf396842,0x3ef15aea,0xbf61c598,0x3e605c13,0xbf79c79d,
0xbd48fb30,0xbf7fb10f,0xbea09ae5,0xbf731447,0x3f800000,0x0,0x3f731447,0xbea09ae5,0x3f4d9f02,0xbf187fc0,0x3f13682a,0xbf514d3d,
0x3e94a031,0xbf74fa0b,0xbcc90ab0,0xbf7fec43,0xbeac7cd4,0xbf710908,0xbf1d7fd1,0xbf49d112,0x3f800000,0x0,0x3f6ed89e,0xbeb8442a,
0x3f3daef9,0xbf2beb4a,0x3ee63375,0xbf64aa59,0x3dc8bd36,0xbf7ec46d,0xbe888e93,0xbf76ba07,0xbf187fc0,0xbf4d9f02,0xbf584853,0xbf08f59b,
0x3f7b14be,0xbe47c5c2,0x3f79c79d,0xbe605c13,0x3f7853f8,0xbe78cfcc,0x3f76ba07,0xbe888e93,0x3f74fa0b,0xbe94a031,0x3f731447,0xbea09ae5,
0x3f710908,0xbeac7cd4,0x3f6ed89e,0xbeb8442a,0x3f54db31,0xbf0e39da,0x3f49d112,0xbf1d7fd1,0x3f3daef9,0xbf2beb4a,0x3f3085bb,0xbf396842,
0x3f226799,0xbf45e403,0x3f13682a,0xbf514d3d,0x3f039c3d,0xbf5b941a,0x3ee63375,0xbf64aa59,0x3f0e39da,0xbf54db31,0x3ee63375,0xbf64aa59,
0x3eac7cd4,0xbf710908,0x3e605c13,0xbf79c79d,0x3dc8bd36,0xbf7ec46d,0xbcc90ab0,0xbf7fec43,0xbe164083,0xbf7d3aac,0xbe888e93,0xbf76ba07,
0x3e47c5c2,0xbf7b14be,0x3cc90ab0,0xbf7fec43,0xbe164083,0xbf7d3aac,0xbea09ae5,0xbf731447,0xbef15aea,0xbf61c598,0xbf1d7fd1,0xbf49d112,
0xbf3daef9,0xbf2beb4a,0xbf584853,0xbf08f59b,0xbe47c5c2,0xbf7b14be,0xbecf7bca,0xbf6a09a7,0xbf187fc0,0xbf4d9f02,0xbf41d870,0xbf273656,
0xbf61c598,0xbef15aea,0xbf76ba07,0xbe888e93,0xbf7fb10f,0xbd48fb30,0xbf7c3b28,0x3e2f10a2,0xbf0e39da,0xbf54db31,0xbf41d870,0xbf273656,
0xbf676bd8,0xbedae880,0xbf7c3b28,0xbe2f10a2,0xbf7ec46d,0x3dc8bd36,0xbf6ed89e,0x3eb8442a,0xbf4d9f02,0x3f187fc0,0xbf1d7fd1,0x3f49d112,
0xbf54db31,0xbf0e39da,0xbf76ba07,0xbe888e93,0xbf7fb10f,0x3d48fb30,0xbf6ed89e,0x3eb8442a,0xbf45e403,0x3f226799,0xbf08f59b,0x3f584853,
0xbe78cfcc,0x3f7853f8,0x3d96a905,0x3f7f4e6d,0xbf7b14be,0xbe47c5c2,0xbf7c3b28,0x3e2f10a2,0xbf5b941a,0x3f039c3d,0xbf1d7fd1,0x3f49d112,
0xbe94a031,0x3f74fa0b,0x3d96a905,0x3f7f4e6d,0x3edae880,0x3f676bd8,0x3f396842,0x3f3085bb,0x80003f80,0x80003f80,0x80003f80,0x80003f80,
0x80003f80,0x80003f80,0x80003f80,0x80003f80,0x80003f80,0x80003f80,0x80003f80,0x80003f80,0x80003f80,0x80003f80,0x80003f80,0x80003f80,
0x3f800000,0x3f800000,0x3f800000,0x3f800000,0x3f800000,0x3f800000,0x3f800000,0x3f800000,0x3f800000,0x3f800000,0x3f800000,0x3f800000,
0x3f800000,0x3f800000,0x3f800000,0x3f800000,0x80003f80,0x3f353f35,0x80003f80,0x3f353f35,0x3f800000,0x3f35bf35,0x3f800000,0x3f35bf35,
0x8000bf80,0xbf35bf35,0x8000bf80,0xbf35bf35,0xbf800000,0xbf353f35,0xbf800000,0xbf353f35,0x3f800000,0x3f35bf35,0x3f800000,0x3f35bf35,
0xbf80,0xbf35bf35,0xbf80,0xbf35bf35,0xbf800000,0xbf353f35,0xbf800000,0xbf353f35,0x3f80,0x3f353f35,0x3f80,0x3f353f35,
0x80003f80,0x3f800000,0x80003f80,0x3f800000,0x8000bf80,0xbf800000,0x8000bf80,0xbf800000,0x80003f80,0x3f800000,0x80003f80,0x3f800000,
0x8000bf80,0xbf800000,0x8000bf80,0xbf800000,0x3f800000,0xbf80,0x3f800000,0xbf80,0xbf800000,0x3f80,0xbf800000,0x3f80,
0x3f800000,0xbf80,0x3f800000,0xbf80,0xbf800000,0x3f80,0xbf800000,0x3f80,0x80003f80,0x3f35bf35,0x80003f80,0x3f35bf35,
0xbf800000,0x3f353f35,0xbf800000,0x3f353f35,0x8000bf80,0xbf353f35,0x8000bf80,0xbf353f35,0x3f800000,0xbf35bf35,0x3f800000,0xbf35bf35,
0x3f800000,0xbf35bf35,0x3f800000,0xbf35bf35,0x3f80,0x3f35bf35,0x3f80,0x3f35bf35,0xbf800000,0x3f353f35,0xbf800000,0x3f353f35,
0xbf80,0xbf353f35,0xbf80,0xbf353f35,0x80003f80,0x3ec43f6d,0x8000bf80,0xbec4bf6d,0x3f353f35,0x3f6d3ec4,0xbf35bf35,0xbf6dbec4,
0x3f800000,0x3f6dbec4,0xbf800000,0xbf6d3ec4,0x3f35bf35,0x3ec4bf6d,0xbf353f35,0xbec43f6d,0x3f800000,0x3f6dbec4,0xbf800000,0xbf6d3ec4,
0x3f35bf35,0x3ec4bf6d,0xbf353f35,0xbec43f6d,0xbf80,0xbec4bf6d,0x3f80,0x3ec43f6d,0xbf35bf35,0xbf6dbec4,0x3f353f35,0x3f6d3ec4,
0x80003f80,0x3f6d3ec4,0x8000bf80,0xbf6dbec4,0x3f35bf35,0xbec4bf6d,0xbf353f35,0x3ec43f6d,0xbf800000,0xbec43f6d,0x3f800000,0x3ec4bf6d,
0x3f353f35,0x3f6dbec4,0xbf35bf35,0xbf6d3ec4,0x3f800000,0x3ec4bf6d,0xbf800000,0xbec43f6d,0xbf35bf35,0xbf6d3ec4,0x3f353f35,0x3f6dbec4,
0x3f80,0x3f6d3ec4,0xbf80,0xbf6dbec4,0x3f35bf35,0xbec4bf6d,0xbf353f35,0x3ec43f6d,0x80003f80,0x3f6dbec4,0x8000bf80,0xbf6d3ec4,
0xbf35bf35,0xbec43f6d,0x3f353f35,0x3ec4bf6d,0x3f800000,0xbec4bf6d,0xbf800000,0x3ec43f6d,0xbf353f35,0x3f6d3ec4,0x3f35bf35,0xbf6dbec4,
0x3f800000,0xbec4bf6d,0xbf800000,0x3ec43f6d,0xbf353f35,0x3f6d3ec4,0x3f35bf35,0xbf6dbec4,0xbf80,0xbf6d3ec4,0x3f80,0x3f6dbec4,
0x3f353f35,0x3ec4bf6d,0xbf35bf35,0xbec43f6d,0x80003f80,0x3ec4bf6d,0x8000bf80,0xbec43f6d,0xbf353f35,0x3f6dbec4,0x3f35bf35,0xbf6d3ec4,
0xbf800000,0x3f6d3ec4,0x3f800000,0xbf6dbec4,0xbf35bf35,0x3ec43f6d,0x3f353f35,0xbec4bf6d,0x3f800000,0xbf6dbec4,0xbf800000,0x3f6d3ec4,
0x3f353f35,0xbec4bf6d,0xbf35bf35,0x3ec43f6d,0x3f80,0x3ec4bf6d,0xbf80,0xbec43f6d,0xbf353f35,0x3f6dbec4,0x3f35bf35,0xbf6d3ec4,
0x80003f80,0x8000bf80,0x80003f80,0x8000bf80,0x80003f80,0x8000bf80,0x80003f80,0x8000bf80,0x80003f80,0x8000bf80,0x80003f80,0x8000bf80,
0x80003f80,0x8000bf80,0x80003f80,0x8000bf80,0x3f800000,0xbf800000,0x3f800000,0xbf800000,0x3f800000,0xbf800000,0x3f800000,0xbf800000,
0x3f800000,0xbf800000,0x3f800000,0xbf800000,0x3f800000,0xbf800000,0x3f800000,0xbf800000,0x80003f80,0xbf35bf35,0x80003f80,0xbf35bf35,
0x3f800000,0xbf353f35,0x3f800000,0xbf353f35,0x8000bf80,0x3f353f35,0x8000bf80,0x3f353f35,0xbf800000,0x3f35bf35,0xbf800000,0x3f35bf35,
0x3f800000,0xbf353f35,0x3f800000,0xbf353f35,0xbf80,0x3f353f35,0xbf80,0x3f353f35,0xbf800000,0x3f35bf35,0xbf800000,0x3f35bf35,
0x3f80,0xbf35bf35,0x3f80,0xbf35bf35,0x80003f80,0xbf800000,0x80003f80,0xbf800000,0x8000bf80,0x3f800000,0x8000bf80,0x3f800000,
0x80003f80,0xbf800000,0x80003f80,0xbf800000,0x8000bf80,0x3f800000,0x8000bf80,0x3f800000,0x3f800000,0x3f80,0x3f800000,0x3f80,
0xbf800000,0xbf80,0xbf800000,0xbf80,0x3f800000,0x3f80,0x3f800000,0x3f80,0xbf800000,0xbf80,0xbf800000,0xbf80,
0x80003f80,0xbf353f35,0x80003f80,0xbf353f35,0xbf800000,0xbf35bf35,0xbf800000,0xbf35bf35,0x8000bf80,0x3f35bf35,0x8000bf80,0x3f35bf35,
0x3f800000,0x3f353f35,0x3f800000,0x3f353f35,0x3f800000,0x3f353f35,0x3f800000,0x3f353f35,0x3f80,0xbf353f35,0x3f80,0xbf353f35,
0xbf800000,0xbf35bf35,0xbf800000,0xbf35bf35,0xbf80,0x3f35bf35,0xbf80,0x3f35bf35,0x80003f80,0xbec4bf6d,0x8000bf80,0x3ec43f6d,
0x3f353f35,0xbf6dbec4,0xbf35bf35,0x3f6d3ec4,0x3f800000,0xbf6d3ec4,0xbf800000,0x3f6dbec4,0x3f35bf35,0xbec43f6d,0xbf353f35,0x3ec4bf6d,
0x3f800000,0xbf6d3ec4,0xbf800000,0x3f6dbec4,0x3f35bf35,0xbec43f6d,0xbf353f35,0x3ec4bf6d,0xbf80,0x3ec43f6d,0x3f80,0xbec4bf6d,
0xbf35bf35,0x3f6d3ec4,0x3f353f35,0xbf6dbec4,0x80003f80,0xbf6dbec4,0x8000bf80,0x3f6d3ec4,0x3f35bf35,0x3ec43f6d,0xbf353f35,0xbec4bf6d,
0xbf800000,0x3ec4bf6d,0x3f800000,0xbec43f6d,0x3f353f35,0xbf6d3ec4,0xbf35bf35,0x3f6dbec4,0x3f800000,0xbec43f6d,0xbf800000,0x3ec4bf6d,
0xbf35bf35,0x3f6dbec4,0x3f353f35,0xbf6d3ec4,0x3f80,0xbf6dbec4,0xbf80,0x3f6d3ec4,0x3f35bf35,0x3ec43f6d,0xbf353f35,0xbec4bf6d,
0x80003f80,0xbf6d3ec4,0x8000bf80,0x3f6dbec4,0xbf35bf35,0x3ec4bf6d,0x3f353f35,0xbec43f6d,0x3f800000,0x3ec43f6d,0xbf800000,0xbec4bf6d,
0xbf353f35,0xbf6dbec4,0x3f35bf35,0x3f6d3ec4,0x3f800000,0x3ec43f6d,0xbf800000,0xbec4bf6d,0xbf353f35,0xbf6dbec4,0x3f35bf35,0x3f6d3ec4,
0xbf80,0x3f6dbec4,0x3f80,0xbf6d3ec4,0x3f353f35,0xbec43f6d,0xbf35bf35,0x3ec4bf6d,0x80003f80,0xbec43f6d,0x8000bf80,0x3ec4bf6d,
0xbf353f35,0xbf6d3ec4,0x3f35bf35,0x3f6dbec4,0xbf800000,0xbf6dbec4,0x3f800000,0x3f6d3ec4,0xbf35bf35,0xbec4bf6d,0x3f353f35,0x3ec43f6d,
0x3f800000,0x3f6d3ec4,0xbf800000,0xbf6dbec4,0x3f353f35,0x3ec43f6d,0xbf35bf35,0xbec4bf6d,0x3f80,0xbec43f6d,0xbf80,0x3ec4bf6d,
0xbf353f35,0xbf6d3ec4,0x3f35bf35,0x3f6dbec4,
};
constexpr int TB_F = 0, TB_E = 512, TB_P2 = 1024;

enum { C_EP = 0, C_Z1 = 32, C_Z2 = 96, C_H3 = 128, C_U = 160, C_TOTAL = 256 };
struct Scratch {
  unsigned cnt[C_TOTAL];
  uint32_t mod[6 * D_ + 384];
  uint32_t z1[120 * 5120];
  uint32_t z2[128 * 4800];
  uint32_t x1[S_ * D_ / 2];
  uint8_t h3[32 * 18 * 4096];
  uint8_t u[72 * D_ * 128];
  uint4 part[128 * 1152];
};
__device__ __align__(1024) Scratch g_s;

#define PF2 8
#define PF2K 16
#define HOLDA 3
#define GOAT 1
#define HOLD1 0
#define XPOS 0
#define HW bulk_commit_wait
#define H3W 0
#define X1K 10
#define NG1 2

#define FAILCNT(k) do {} while (0)
#define CK(k) do {} while (0)
#define CKX(k) do {} while (0)
#define TS(k) do {} while (0)
#define TSC(k) do {} while (0)
struct Maps { CUtensorMap w1a, w1b, w2, x1, out, z1, z2, h3, wf[4], wm; };
struct Params {
  const __nv_bfloat16 *x, *c, *wmod;
  Scratch* s;
  const uint4* tab;
  const __nv_bfloat16 *wr, *wi, *w1, *w2, *b1, *b2;
};

__device__ __forceinline__ uint32_t smem_u32(const void* p) { return (uint32_t)__cvta_generic_to_shared(p); }
__device__ __forceinline__ void mbar_init(uint32_t b, int c) { asm volatile("mbarrier.init.shared::cta.b64 [%0], %1;" ::"r"(b), "r"(c)); }
__device__ __forceinline__ void mbar_expect(uint32_t b, int bytes) { asm volatile("mbarrier.arrive.expect_tx.shared::cta.b64 _, [%0], %1;" ::"r"(b), "r"(bytes) : "memory"); }
__device__ __forceinline__ void mbar_arrive(uint32_t b) { asm volatile("mbarrier.arrive.shared::cta.b64 _, [%0];" ::"r"(b) : "memory"); }
#define MBAR_WAIT(SEM)                                                                                                         \
  asm volatile("{\n.reg .pred p;\n.reg .u32 it;\nmov.u32 it, 0;\nW:\nmbarrier.try_wait.parity" SEM ".shared::cta.b64 p, [%0], %1;\n" \
               "@p bra.uni D;\nadd.u32 it, it, 1;\nsetp.lt.u32 p, it, 0x400000;\n@p bra.uni W;\ntrap;\nD:\n}" ::"r"(b), "r"(ph) : "memory")
__device__ __forceinline__ void mbar_wait(uint32_t b, int ph) { MBAR_WAIT(""); }
__device__ __forceinline__ void tma2d(uint32_t dst, const CUtensorMap* m, int c0, int c1, uint32_t bar) {
  asm volatile("cp.async.bulk.tensor.2d.shared::cluster.global.mbarrier::complete_tx::bytes [%0], [%1, {%3, %4}], [%2];" ::"r"(dst), "l"(m), "r"(bar), "r"(c0), "r"(c1) : "memory");
}
__device__ __forceinline__ uint64_t pol_ef() { uint64_t p; asm("createpolicy.fractional.L2::evict_first.b64 %0, 1.0;" : "=l"(p)); return p; }
__device__ __forceinline__ void tma3d_ef(uint32_t dst, const CUtensorMap* m, int c1, int c2, uint32_t bar) {
  asm volatile("cp.async.bulk.tensor.3d.shared::cluster.global.mbarrier::complete_tx::bytes.L2::cache_hint [%0], [%1, {%3, %4, %5}], [%2], %6;" ::"r"(dst), "l"(m), "r"(bar), "r"(0), "r"(c1), "r"(c2), "l"(pol_ef()) : "memory");
}
__device__ __forceinline__ void tma4d_ef(uint32_t dst, const CUtensorMap* m, int c1, int c2, int c3, uint32_t bar) {
  asm volatile("cp.async.bulk.tensor.4d.shared::cluster.global.mbarrier::complete_tx::bytes.L2::cache_hint [%0], [%1, {%3, %7, %4, %5}], [%2], %6;" ::"r"(dst), "l"(m), "r"(bar), "r"(0), "r"(c2), "r"(c3), "l"(pol_ef()), "r"(c1) : "memory");
}
__device__ __forceinline__ void bulk_ld(uint32_t dst, const void* src, int bytes, uint32_t bar) {
  asm volatile("cp.async.bulk.shared::cluster.global.mbarrier::complete_tx::bytes [%0], [%1], %2, [%3];" ::"r"(dst), "l"(src), "r"(bytes), "r"(bar) : "memory");
}
__device__ __forceinline__ void bulk_st(void* dst, uint32_t src, int bytes) {
  asm volatile("cp.async.bulk.global.shared::cta.bulk_group [%0], [%1], %2;" ::"l"(dst), "r"(src), "r"(bytes) : "memory");
}
__device__ __forceinline__ void tma_st2d(const CUtensorMap* m, uint32_t src, int c0, int c1) {
  asm volatile("cp.async.bulk.tensor.2d.global.shared::cta.bulk_group [%0, {%2, %3}], [%1];" ::"l"(m), "r"(src), "r"(c0), "r"(c1) : "memory");
}
__device__ __forceinline__ void tma_st3d(const CUtensorMap* m, uint32_t src, int c0, int c1, int c2) {
  asm volatile("cp.async.bulk.tensor.3d.global.shared::cta.bulk_group [%0, {%2, %3, %4}], [%1];" ::"l"(m), "r"(src), "r"(c0), "r"(c1), "r"(c2) : "memory");
}
__device__ __forceinline__ void bulk_commit_wait_read() {
  asm volatile("cp.async.bulk.commit_group;" ::: "memory");
  asm volatile("cp.async.bulk.wait_group.read 0;" ::: "memory");
}
__device__ __forceinline__ void bulk_commit_wait() {
  asm volatile("cp.async.bulk.commit_group;" ::: "memory");
  asm volatile("cp.async.bulk.wait_group 0;" ::: "memory");
}
__device__ __forceinline__ void prefetch_l2(const void* p, int bytes) {
  asm volatile("cp.async.bulk.prefetch.L2.global [%0], %1;" ::"l"(p), "r"(bytes) : "memory");
}
__device__ __forceinline__ void wg_fence() { asm volatile("wgmma.fence.sync.aligned;" ::: "memory"); }
__device__ __forceinline__ void wg_commit() { asm volatile("wgmma.commit_group.sync.aligned;" ::: "memory"); }
template <int N> __device__ __forceinline__ void wg_wait() { asm volatile("wgmma.wait_group.sync.aligned %0;" ::"n"(N) : "memory"); }
template <int N> __device__ __forceinline__ void reg_fence(float (&d)[N]) {
#pragma unroll
  for (int i = 0; i < N; i++) asm volatile("" : "+f"(d[i])::"memory");
}
__device__ __forceinline__ void fence_async_smem() { asm volatile("fence.proxy.async.shared::cta;" ::: "memory"); }
__device__ __forceinline__ void fence_async_glb() { asm volatile("fence.proxy.async.global;" ::: "memory"); }
__device__ __forceinline__ uint32_t ld_rlx(const void* p) { uint32_t v; asm volatile("ld.relaxed.gpu.global.b32 %0, [%1];" : "=r"(v) : "l"(p) : "memory"); return v; }
__device__ __forceinline__ uint2 ld_rlx2(const void* p) { uint2 v; asm volatile("ld.relaxed.gpu.global.v2.b32 {%0,%1}, [%2];" : "=r"(v.x), "=r"(v.y) : "l"(p) : "memory"); return v; }
__device__ __forceinline__ uint4 ld_rlx4(const void* p) { uint4 v; asm volatile("ld.relaxed.gpu.global.v4.b32 {%0,%1,%2,%3}, [%4];" : "=r"(v.x), "=r"(v.y), "=r"(v.z), "=r"(v.w) : "l"(p) : "memory"); return v; }
__device__ __forceinline__ uint32_t ld_nc(const void* p) { uint32_t v; asm volatile("ld.global.nc.L1::no_allocate.b32 %0, [%1];" : "=r"(v) : "l"(p) : "memory"); return v; }
__device__ __forceinline__ uint32_t lds(uint32_t a) { uint32_t v; asm volatile("ld.shared.b32 %0, [%1];" : "=r"(v) : "r"(a) : "memory"); return v; }
__device__ __forceinline__ uint2 lds2(uint32_t a) { uint2 v; asm volatile("ld.shared.v2.b32 {%0,%1}, [%2];" : "=r"(v.x), "=r"(v.y) : "r"(a) : "memory"); return v; }
__device__ __forceinline__ uint4 lds4(uint32_t a) { uint4 v; asm volatile("ld.shared.v4.b32 {%0,%1,%2,%3}, [%4];" : "=r"(v.x), "=r"(v.y), "=r"(v.z), "=r"(v.w) : "r"(a) : "memory"); return v; }
__device__ __forceinline__ float lds_bf(uint32_t a) { uint32_t v; asm volatile("ld.shared.u16 %0, [%1];" : "=r"(v) : "r"(a) : "memory"); return __uint_as_float(v << 16); }
__device__ __forceinline__ void sts(uint32_t a, uint32_t v) { asm volatile("st.shared.b32 [%0], %1;" ::"r"(a), "r"(v) : "memory"); }
__device__ __forceinline__ void sts2(uint32_t a, uint32_t v0, uint32_t v1) { asm volatile("st.shared.v2.b32 [%0], {%1,%2};" ::"r"(a), "r"(v0), "r"(v1) : "memory"); }
__device__ __forceinline__ void sts4(uint32_t a, uint32_t v0, uint32_t v1, uint32_t v2, uint32_t v3) { asm volatile("st.shared.v4.b32 [%0], {%1,%2,%3,%4};" ::"r"(a), "r"(v0), "r"(v1), "r"(v2), "r"(v3) : "memory"); }
__device__ __forceinline__ void bar_sync(int id, int n) { asm volatile("bar.sync %0, %1;" ::"r"(id), "r"(n) : "memory"); }
__device__ __forceinline__ void bar_arrive(int id, int n) { asm volatile("bar.arrive %0, %1;" ::"r"(id), "r"(n) : "memory"); }
__device__ __forceinline__ void red_add(unsigned* p, unsigned v) { asm volatile("red.relaxed.gpu.global.add.u32 [%0], %1;" ::"l"(p), "r"(v) : "memory"); }
__device__ __forceinline__ bool any(bool p) { return __any_sync(0xffffffffu, p); }
constexpr int SPIN_MAX = 1 << 20;
__device__ __forceinline__ void wait_cnt(const unsigned* p, unsigned target) {
  int it = 0;
  while (any((int)(ld_rlx(p) - target) < 0) && ++it < SPIN_MAX) {}
}
__device__ __forceinline__ uint32_t pack_bf16(float lo, float hi) { uint32_t r; asm("cvt.rn.bf16x2.f32 %0, %1, %2;" : "=r"(r) : "f"(hi), "f"(lo)); return r; }
__device__ __forceinline__ float bf_lo(uint32_t v) { return __uint_as_float(v << 16); }
__device__ __forceinline__ float bf_hi(uint32_t v) { return __uint_as_float(v & 0xffff0000u); }
__device__ __forceinline__ uint32_t hadd2(uint32_t a, uint32_t b) { uint32_t r; asm("add.rn.bf16x2 %0, %1, %2;" : "=r"(r) : "r"(a), "r"(b)); return r; }
__device__ __forceinline__ uint32_t hmul2(uint32_t a, uint32_t b) { uint32_t r; asm("mul.rn.bf16x2 %0, %1, %2;" : "=r"(r) : "r"(a), "r"(b)); return r; }
__device__ __forceinline__ uint32_t hfma2(uint32_t a, uint32_t b, uint32_t c) { uint32_t r; asm("fma.rn.bf16x2 %0, %1, %2, %3;" : "=r"(r) : "r"(a), "r"(b), "r"(c)); return r; }
__device__ __forceinline__ float rbf(float x) { uint32_t r; asm("cvt.rn.bf16x2.f32 %0, %1, %2;" : "=r"(r) : "f"(x), "f"(0.0f)); return __uint_as_float(r); }
__device__ __forceinline__ void stmatrix4(uint32_t a, uint32_t r0, uint32_t r1, uint32_t r2, uint32_t r3) {
  asm volatile("stmatrix.sync.aligned.m8n8.x4.shared.b16 [%0], {%1,%2,%3,%4};" ::"r"(a), "r"(r0), "r"(r1), "r"(r2), "r"(r3) : "memory");
}
__device__ __forceinline__ void stmatrix2(uint32_t a, uint32_t r0, uint32_t r1) {
  asm volatile("stmatrix.sync.aligned.m8n8.x2.shared.b16 [%0], {%1,%2};" ::"r"(a), "r"(r0), "r"(r1) : "memory");
}
__device__ __forceinline__ void stmatrix4t(uint32_t a, uint32_t r0, uint32_t r1, uint32_t r2, uint32_t r3) {
  asm volatile("stmatrix.sync.aligned.m8n8.x4.trans.shared.b16 [%0], {%1,%2,%3,%4};" ::"r"(a), "r"(r0), "r"(r1), "r"(r2), "r"(r3) : "memory");
}
__device__ __forceinline__ uint32_t movm(uint32_t a) { uint32_t r; asm("movmatrix.sync.aligned.m8n8.trans.b16 %0, %1;" : "=r"(r) : "r"(a)); return r; }
template <bool ACC> __device__ __forceinline__ void mma16(float* d, uint32_t a0, uint32_t a1, uint32_t a2, uint32_t a3, uint32_t b0, uint32_t b1) {
  if (ACC) asm("mma.sync.aligned.m16n8k16.row.col.f32.bf16.bf16.f32 {%0,%1,%2,%3}, {%4,%5,%6,%7}, {%8,%9}, {%0,%1,%2,%3};"
               : "+f"(d[0]), "+f"(d[1]), "+f"(d[2]), "+f"(d[3]) : "r"(a0), "r"(a1), "r"(a2), "r"(a3), "r"(b0), "r"(b1));
  else asm("mma.sync.aligned.m16n8k16.row.col.f32.bf16.bf16.f32 {%0,%1,%2,%3}, {%4,%5,%6,%7}, {%8,%9}, {%10,%10,%10,%10};"
           : "=f"(d[0]), "=f"(d[1]), "=f"(d[2]), "=f"(d[3]) : "r"(a0), "r"(a1), "r"(a2), "r"(a3), "r"(b0), "r"(b1), "f"(0.f));
}
__device__ __forceinline__ uint32_t pin(uint32_t v) { uint32_t r; asm volatile("shfl.sync.bfly.b32 %0, %1, 0, 31, 0xffffffff;" : "=r"(r) : "r"(v)); return r; }
__device__ __forceinline__ uint32_t set_tag(uint32_t w, uint32_t tag) { uint32_t r; asm("lop3.b32 %0, %1, 0xfffffffe, %2, 0xea;" : "=r"(r) : "r"(w), "r"(tag)); return r; }
__device__ __forceinline__ uint32_t diff2(uint32_t a, uint32_t b, uint32_t tag) { uint32_t r; asm("lop3.b32 %0, %1, %2, %3, 0x7e;" : "=r"(r) : "r"(a), "r"(b), "r"(tag)); return r; }
__device__ __forceinline__ float2 cmul(float2 a, float2 b) { return make_float2(a.x * b.x - a.y * b.y, a.x * b.y + a.y * b.x); }

template<int TB> __device__ __forceinline__ void wgmma_ss_160_0(float (&d)[80], uint32_t al, uint32_t ah, uint32_t bl, uint32_t bh) {
  asm volatile("{\n.reg .b64 da, db;\nmov.b64 da, {%80, %81};\nmov.b64 db, {%82, %83};\n"
    "wgmma.mma_async.sync.aligned.m64n160k16.f32.bf16.bf16 {%0,%1,%2,%3,%4,%5,%6,%7,%8,%9,%10,%11,%12,%13,%14,%15,%16,%17,%18,%19,%20,%21,%22,%23,%24,%25,%26,%27,%28,%29,%30,%31,%32,%33,%34,%35,%36,%37,%38,%39,%40,%41,%42,%43,%44,%45,%46,%47,%48,%49,%50,%51,%52,%53,%54,%55,%56,%57,%58,%59,%60,%61,%62,%63,%64,%65,%66,%67,%68,%69,%70,%71,%72,%73,%74,%75,%76,%77,%78,%79}, da, db, 1, 1, 1, 1, %84;\n}\n"
    : "+f"(d[0]),"+f"(d[1]),"+f"(d[2]),"+f"(d[3]),"+f"(d[4]),"+f"(d[5]),"+f"(d[6]),"+f"(d[7]),"+f"(d[8]),"+f"(d[9]),"+f"(d[10]),"+f"(d[11]),"+f"(d[12]),"+f"(d[13]),"+f"(d[14]),"+f"(d[15]),"+f"(d[16]),"+f"(d[17]),"+f"(d[18]),"+f"(d[19]),"+f"(d[20]),"+f"(d[21]),"+f"(d[22]),"+f"(d[23]),"+f"(d[24]),"+f"(d[25]),"+f"(d[26]),"+f"(d[27]),"+f"(d[28]),"+f"(d[29]),"+f"(d[30]),"+f"(d[31]),"+f"(d[32]),"+f"(d[33]),"+f"(d[34]),"+f"(d[35]),"+f"(d[36]),"+f"(d[37]),"+f"(d[38]),"+f"(d[39]),"+f"(d[40]),"+f"(d[41]),"+f"(d[42]),"+f"(d[43]),"+f"(d[44]),"+f"(d[45]),"+f"(d[46]),"+f"(d[47]),"+f"(d[48]),"+f"(d[49]),"+f"(d[50]),"+f"(d[51]),"+f"(d[52]),"+f"(d[53]),"+f"(d[54]),"+f"(d[55]),"+f"(d[56]),"+f"(d[57]),"+f"(d[58]),"+f"(d[59]),"+f"(d[60]),"+f"(d[61]),"+f"(d[62]),"+f"(d[63]),"+f"(d[64]),"+f"(d[65]),"+f"(d[66]),"+f"(d[67]),"+f"(d[68]),"+f"(d[69]),"+f"(d[70]),"+f"(d[71]),"+f"(d[72]),"+f"(d[73]),"+f"(d[74]),"+f"(d[75]),"+f"(d[76]),"+f"(d[77]),"+f"(d[78]),"+f"(d[79])
    : "r"(al), "r"(ah), "r"(bl), "r"(bh), "n"(TB));
}
template<int TB> __device__ __forceinline__ void wgmma_ss_144_0(float (&d)[80], uint32_t al, uint32_t ah, uint32_t bl, uint32_t bh) {
  asm volatile("{\n.reg .b64 da, db;\nmov.b64 da, {%72, %73};\nmov.b64 db, {%74, %75};\n"
    "wgmma.mma_async.sync.aligned.m64n144k16.f32.bf16.bf16 {%0,%1,%2,%3,%4,%5,%6,%7,%8,%9,%10,%11,%12,%13,%14,%15,%16,%17,%18,%19,%20,%21,%22,%23,%24,%25,%26,%27,%28,%29,%30,%31,%32,%33,%34,%35,%36,%37,%38,%39,%40,%41,%42,%43,%44,%45,%46,%47,%48,%49,%50,%51,%52,%53,%54,%55,%56,%57,%58,%59,%60,%61,%62,%63,%64,%65,%66,%67,%68,%69,%70,%71}, da, db, 1, 1, 1, 1, %76;\n}\n"
    : "+f"(d[0]),"+f"(d[1]),"+f"(d[2]),"+f"(d[3]),"+f"(d[4]),"+f"(d[5]),"+f"(d[6]),"+f"(d[7]),"+f"(d[8]),"+f"(d[9]),"+f"(d[10]),"+f"(d[11]),"+f"(d[12]),"+f"(d[13]),"+f"(d[14]),"+f"(d[15]),"+f"(d[16]),"+f"(d[17]),"+f"(d[18]),"+f"(d[19]),"+f"(d[20]),"+f"(d[21]),"+f"(d[22]),"+f"(d[23]),"+f"(d[24]),"+f"(d[25]),"+f"(d[26]),"+f"(d[27]),"+f"(d[28]),"+f"(d[29]),"+f"(d[30]),"+f"(d[31]),"+f"(d[32]),"+f"(d[33]),"+f"(d[34]),"+f"(d[35]),"+f"(d[36]),"+f"(d[37]),"+f"(d[38]),"+f"(d[39]),"+f"(d[40]),"+f"(d[41]),"+f"(d[42]),"+f"(d[43]),"+f"(d[44]),"+f"(d[45]),"+f"(d[46]),"+f"(d[47]),"+f"(d[48]),"+f"(d[49]),"+f"(d[50]),"+f"(d[51]),"+f"(d[52]),"+f"(d[53]),"+f"(d[54]),"+f"(d[55]),"+f"(d[56]),"+f"(d[57]),"+f"(d[58]),"+f"(d[59]),"+f"(d[60]),"+f"(d[61]),"+f"(d[62]),"+f"(d[63]),"+f"(d[64]),"+f"(d[65]),"+f"(d[66]),"+f"(d[67]),"+f"(d[68]),"+f"(d[69]),"+f"(d[70]),"+f"(d[71])
    : "r"(al), "r"(ah), "r"(bl), "r"(bh), "n"(TB));
}
template<int TB> __device__ __forceinline__ void wgmma_ss_96_0(float (&d)[80], uint32_t al, uint32_t ah, uint32_t bl, uint32_t bh) {
  asm volatile("{\n.reg .b64 da, db;\nmov.b64 da, {%48, %49};\nmov.b64 db, {%50, %51};\n"
    "wgmma.mma_async.sync.aligned.m64n96k16.f32.bf16.bf16 {%0,%1,%2,%3,%4,%5,%6,%7,%8,%9,%10,%11,%12,%13,%14,%15,%16,%17,%18,%19,%20,%21,%22,%23,%24,%25,%26,%27,%28,%29,%30,%31,%32,%33,%34,%35,%36,%37,%38,%39,%40,%41,%42,%43,%44,%45,%46,%47}, da, db, 1, 1, 1, 1, %52;\n}\n"
    : "+f"(d[0]),"+f"(d[1]),"+f"(d[2]),"+f"(d[3]),"+f"(d[4]),"+f"(d[5]),"+f"(d[6]),"+f"(d[7]),"+f"(d[8]),"+f"(d[9]),"+f"(d[10]),"+f"(d[11]),"+f"(d[12]),"+f"(d[13]),"+f"(d[14]),"+f"(d[15]),"+f"(d[16]),"+f"(d[17]),"+f"(d[18]),"+f"(d[19]),"+f"(d[20]),"+f"(d[21]),"+f"(d[22]),"+f"(d[23]),"+f"(d[24]),"+f"(d[25]),"+f"(d[26]),"+f"(d[27]),"+f"(d[28]),"+f"(d[29]),"+f"(d[30]),"+f"(d[31]),"+f"(d[32]),"+f"(d[33]),"+f"(d[34]),"+f"(d[35]),"+f"(d[36]),"+f"(d[37]),"+f"(d[38]),"+f"(d[39]),"+f"(d[40]),"+f"(d[41]),"+f"(d[42]),"+f"(d[43]),"+f"(d[44]),"+f"(d[45]),"+f"(d[46]),"+f"(d[47])
    : "r"(al), "r"(ah), "r"(bl), "r"(bh), "n"(TB));
}
template<int TB> __device__ __forceinline__ void wgmma_ss_48_48(float (&d)[80], uint32_t al, uint32_t ah, uint32_t bl, uint32_t bh) {
  asm volatile("{\n.reg .b64 da, db;\nmov.b64 da, {%24, %25};\nmov.b64 db, {%26, %27};\n"
    "wgmma.mma_async.sync.aligned.m64n48k16.f32.bf16.bf16 {%0,%1,%2,%3,%4,%5,%6,%7,%8,%9,%10,%11,%12,%13,%14,%15,%16,%17,%18,%19,%20,%21,%22,%23}, da, db, 1, 1, 1, 1, %28;\n}\n"
    : "+f"(d[48]),"+f"(d[49]),"+f"(d[50]),"+f"(d[51]),"+f"(d[52]),"+f"(d[53]),"+f"(d[54]),"+f"(d[55]),"+f"(d[56]),"+f"(d[57]),"+f"(d[58]),"+f"(d[59]),"+f"(d[60]),"+f"(d[61]),"+f"(d[62]),"+f"(d[63]),"+f"(d[64]),"+f"(d[65]),"+f"(d[66]),"+f"(d[67]),"+f"(d[68]),"+f"(d[69]),"+f"(d[70]),"+f"(d[71])
    : "r"(al), "r"(ah), "r"(bl), "r"(bh), "n"(TB));
}
__device__ __forceinline__ void wgmma_rs_72(float (&d)[36], uint32_t a0, uint32_t a1, uint32_t a2, uint32_t a3, uint32_t bl, uint32_t bh, int sd) {
  asm volatile("{\n.reg .pred p;\n.reg .b64 db;\nsetp.ne.b32 p, %42, 0;\nmov.b64 db, {%40, %41};\n"
    "wgmma.mma_async.sync.aligned.m64n72k16.f32.bf16.bf16 {%0,%1,%2,%3,%4,%5,%6,%7,%8,%9,%10,%11,%12,%13,%14,%15,%16,%17,%18,%19,%20,%21,%22,%23,%24,%25,%26,%27,%28,%29,%30,%31,%32,%33,%34,%35}, {%36,%37,%38,%39}, db, p, 1, 1, 1;\n}\n"
    : "+f"(d[0]),"+f"(d[1]),"+f"(d[2]),"+f"(d[3]),"+f"(d[4]),"+f"(d[5]),"+f"(d[6]),"+f"(d[7]),"+f"(d[8]),"+f"(d[9]),"+f"(d[10]),"+f"(d[11]),"+f"(d[12]),"+f"(d[13]),"+f"(d[14]),"+f"(d[15]),"+f"(d[16]),"+f"(d[17]),"+f"(d[18]),"+f"(d[19]),"+f"(d[20]),"+f"(d[21]),"+f"(d[22]),"+f"(d[23]),"+f"(d[24]),"+f"(d[25]),"+f"(d[26]),"+f"(d[27]),"+f"(d[28]),"+f"(d[29]),"+f"(d[30]),"+f"(d[31]),"+f"(d[32]),"+f"(d[33]),"+f"(d[34]),"+f"(d[35])
    : "r"(a0), "r"(a1), "r"(a2), "r"(a3), "r"(bl), "r"(bh), "r"(sd));
}
__device__ __forceinline__ void wgmma_rs_48(float (&d)[24], uint32_t a0, uint32_t a1, uint32_t a2, uint32_t a3, uint32_t bl, uint32_t bh, int sd) {
  asm volatile("{\n.reg .pred p;\n.reg .b64 db;\nsetp.ne.b32 p, %30, 0;\nmov.b64 db, {%28, %29};\n"
    "wgmma.mma_async.sync.aligned.m64n48k16.f32.bf16.bf16 {%0,%1,%2,%3,%4,%5,%6,%7,%8,%9,%10,%11,%12,%13,%14,%15,%16,%17,%18,%19,%20,%21,%22,%23}, {%24,%25,%26,%27}, db, p, 1, 1, 1;\n}\n"
    : "+f"(d[0]),"+f"(d[1]),"+f"(d[2]),"+f"(d[3]),"+f"(d[4]),"+f"(d[5]),"+f"(d[6]),"+f"(d[7]),"+f"(d[8]),"+f"(d[9]),"+f"(d[10]),"+f"(d[11]),"+f"(d[12]),"+f"(d[13]),"+f"(d[14]),"+f"(d[15]),"+f"(d[16]),"+f"(d[17]),"+f"(d[18]),"+f"(d[19]),"+f"(d[20]),"+f"(d[21]),"+f"(d[22]),"+f"(d[23])
    : "r"(a0), "r"(a1), "r"(a2), "r"(a3), "r"(bl), "r"(bh), "r"(sd));
}
template<int N,int OFF,int TB> __device__ __forceinline__ void wgmma_ss(float (&d)[80], uint32_t al, uint32_t ah, uint32_t bl, uint32_t bh) {
  if constexpr (N==160) wgmma_ss_160_0<TB>(d, al, ah, bl, bh);
  else if constexpr (N==144) wgmma_ss_144_0<TB>(d, al, ah, bl, bh);
  else if constexpr (N==96) wgmma_ss_96_0<TB>(d, al, ah, bl, bh);
  else if constexpr (N==48) wgmma_ss_48_48<TB>(d, al, ah, bl, bh);
}

__device__ __forceinline__ void dft3(float2& a, float2& b, float2& c) {
  const float s = 0.86602540378443864676f;
  float2 t = make_float2(b.x + c.x, b.y + c.y), d = make_float2(b.x - c.x, b.y - c.y);
  float2 m = make_float2(fmaf(-0.5f, t.x, a.x), fmaf(-0.5f, t.y, a.y));
  a = make_float2(a.x + t.x, a.y + t.y);
  b = make_float2(fmaf(s, d.y, m.x), fmaf(-s, d.x, m.y));
  c = make_float2(fmaf(-s, d.y, m.x), fmaf(s, d.x, m.y));
}
__device__ __forceinline__ void dft9(float2 (&x)[9]) {
  const float2 w1 = make_float2(0.76604444311897803520f, -0.64278760968653932632f);
  const float2 w2 = make_float2(0.17364817766693034885f, -0.98480775301220805937f);
  const float2 w4 = make_float2(-0.93969262078590838405f, -0.34202014332566873304f);
  dft3(x[0], x[3], x[6]); dft3(x[1], x[4], x[7]); dft3(x[2], x[5], x[8]);
  x[4] = cmul(x[4], w1); x[7] = cmul(x[7], w2); x[5] = cmul(x[5], w2); x[8] = cmul(x[8], w4);
  dft3(x[0], x[1], x[2]); dft3(x[3], x[4], x[5]); dft3(x[6], x[7], x[8]);
  float2 t;
  t = x[1]; x[1] = x[3]; x[3] = t;
  t = x[2]; x[2] = x[6]; x[6] = t;
  t = x[5]; x[5] = x[7]; x[7] = t;
}

__device__ __forceinline__ int mod_pos(int u, int i) { return 16 * u + (u < 72 ? 2 * (i & 7) + (i >> 3) : i); }
__device__ __forceinline__ void mod_fma(float (&acc)[8], float sc, const uint4& w) {
  acc[0] = fmaf(sc, bf_lo(w.x), acc[0]); acc[1] = fmaf(sc, bf_hi(w.x), acc[1]);
  acc[2] = fmaf(sc, bf_lo(w.y), acc[2]); acc[3] = fmaf(sc, bf_hi(w.y), acc[3]);
  acc[4] = fmaf(sc, bf_lo(w.z), acc[4]); acc[5] = fmaf(sc, bf_hi(w.z), acc[5]);
  acc[6] = fmaf(sc, bf_lo(w.w), acc[6]); acc[7] = fmaf(sc, bf_hi(w.w), acc[7]);
}
__device__ __forceinline__ void mod_finish(const Params& p, float (&acc)[8], int u, int t128, uint32_t red, uint32_t tag) {
#pragma unroll
  for (int n = 4, o = 2; n; n >>= 1, o <<= 1) {
    const bool up = t128 & o;
#pragma unroll
    for (int e = 0; e < n; e++) acc[e] = (up ? acc[e + n] : acc[e]) + __shfl_xor_sync(0xffffffffu, up ? acc[e] : acc[e + n], o);
  }
  acc[0] += __shfl_xor_sync(0xffffffffu, acc[0], 16);
  const int col = 8 * (t128 & 1) + 2 * (t128 & 2) + ((t128 >> 1) & 2) + ((t128 >> 3) & 1);
  if (!(t128 & 16)) sts(red + (col * 4 + (t128 >> 5)) * 4, __float_as_uint(acc[0]));
  bar_sync(4, 128);
  if (t128 < 16) {
    const uint4 v = lds4(red + t128 * 16);
    float m = rbf((__uint_as_float(v.x) + __uint_as_float(v.y)) + (__uint_as_float(v.z) + __uint_as_float(v.w)));
    const int kind = u / 36;
    if (kind == 0) m *= 16.0f;
    if (kind == 1 || kind == 4) m = rbf(1.0f + m);
    p.s->mod[mod_pos(u, t128)] = __float_as_uint(m) | tag;
  }
}

__device__ __forceinline__ void ln_stats2(const float (&a)[18], const float (&b)[18], float sc, float& oa, float& ra, float& ob, float& rb) {
  float v[4] = {0.f, 0.f, 0.f, 0.f}, w[4] = {0.f, 0.f, 0.f, 0.f};
#pragma unroll
  for (int i = 0; i < 18; i += 2) {
    v[0] += a[i]; v[1] = fmaf(a[i], a[i], v[1]); v[2] += b[i]; v[3] = fmaf(b[i], b[i], v[3]);
    w[0] += a[i + 1]; w[1] = fmaf(a[i + 1], a[i + 1], w[1]); w[2] += b[i + 1]; w[3] = fmaf(b[i + 1], b[i + 1], w[3]);
  }
#pragma unroll
  for (int e = 0; e < 4; e++) v[e] += w[e];
#pragma unroll
  for (int o = 16; o; o >>= 1) {
#pragma unroll
    for (int e = 0; e < 4; e++) v[e] += __shfl_xor_sync(0xffffffffu, v[e], o);
  }
  const float ma = v[0] * (1.0f / D_), mb = v[2] * (1.0f / D_);
  ra = sc * rsqrtf(fmaxf(fmaf(-ma, ma, v[1] * (1.0f / D_)), 0.f) + 1e-5f);
  rb = sc * rsqrtf(fmaxf(fmaf(-mb, mb, v[3] * (1.0f / D_)), 0.f) + 1e-5f);
  oa = -ma * ra; ob = -mb * rb;
}

__device__ __forceinline__ float tmat(int c, int q, int j) {
  const int ph = q == 1 ? 1024 * j : (q >> 1) * (c + 128 * j) + 512 * (q & 1);
  return __cosf((float)(((ph + 1024) & 2047) - 1024) * (6.283185307179586f / 2048.0f));
}
__device__ __forceinline__ uint32_t line_off(int k1, int kap, int pi, int f) {
  int kd = 64 * k1 + 9 * kap;
  if (kap == 0 && k1 > 4) kd -= 288;
  if (kd >= D_) kd -= D_;
  return pi * 2400 + ((min(kd, D_ - kd) ^ f) << 3);
}

constexpr int JSK = 5;
struct Ring { uint32_t st, ph; };
template <bool G2, class T> __device__ __forceinline__ void ring_next(T& st, T& ph) {
  if (++st == NST) st = 0;
  ph ^= ((G2 ? 0xDu : 0x1u) >> st) & 1;
}
__device__ __forceinline__ void arrive_if(uint32_t a, uint32_t p) {
  asm volatile("{\n.reg .pred p;\nsetp.ne.u32 p, %1, 0;\n@p mbarrier.arrive.shared::cta.b64 _, [%0];\n}" ::"r"(a), "r"(p) : "memory");
}
template <int NA> __device__ __forceinline__ void reg_fence_n(float (&d)[80]) {
#pragma unroll
  for (int i = 0; i < NA; i++) asm volatile("" : "+f"(d[i])::"memory");
}
template <int MODE>
__device__ __forceinline__ void gemm_main(float (&acc)[80], uint32_t da0, uint32_t da1, uint32_t db0, uint32_t db1, int wg, Ring& rg, uint32_t full0,
                                          uint32_t* x1p, const uint32_t (&xr)[18]) {
  static_assert(JSK == NST - 1, "the held slot is the first one that is not refilled by GEMM1");
  constexpr int NKB = MODE == 3 ? 36 : 32;
  constexpr uint32_t HA = 0x40000040u, HB = MODE == 3 ? 0x40000040u : 0x80000020u;
  constexpr uint32_t KA = 2048 >> 4, KB = MODE == 3 ? (32 >> 4) : (1024 >> 4);
  constexpr int NA = MODE ? 72 : 80;
  const uint32_t t = threadIdx.x & 127;
  const uint32_t eb = full0 + 8 * NST;
  uint32_t pb = 0, rel = t == 0, prel = 0;
  int n = MODE == 3 ? NKB - JSK : X1K + 2 * wg;
#pragma unroll 1
  for (int pass = MODE == 3 ? 0 : -1;; pass++) {
#pragma unroll 1
    do {
      const uint32_t so = rg.st * (STAGE >> 4);
      mbar_wait(full0 + 8 * rg.st, rg.ph);
      reg_fence_n<NA>(acc);
      wg_fence();
#pragma unroll
      for (int k = 0; k < 4; k++) {
        if (MODE == 0) wgmma_ss<160, 0, 1>(acc, da0 + so + k * KA, HA, db0 + so + k * KB, HB);
        else if (MODE == 3) wgmma_ss<144, 0, 0>(acc, da0 + so + k * KA, HA, db0 + so + k * KB, HB);
        else {
          wgmma_ss<96, 0, 1>(acc, da0 + so + k * KA, HA, db0 + so + k * KB, HB);
          wgmma_ss<48, 48, 1>(acc, da1 + so + k * KA, HA, db1 + so + k * KB, HB);
        }
      }
      wg_commit();
      wg_wait<1>();
      reg_fence_n<NA>(acc);
      arrive_if(pb, prel);
      pb = eb + 8 * rg.st; prel = rel;
      ring_next<MODE == 3>(rg.st, rg.ph);
    } while (--n);
    if (pass == 2 - wg) break;
    if (MODE != 3 && pass < 0) {
      if (blockIdx.x < 128) {
#pragma unroll
        for (int i = 0; i < 9; i++) { x1p[32 * i] = xr[i]; x1p[128 * 288 + 32 * i] = xr[9 + i]; }
      }
      n = NKB - JSK - X1K - 2 * wg;
      continue;
    }
    n = 1;
    if (pass == 0) {
      if (MODE != 3) prel = rel & wg;
      else rel = 0;
      n = JSK - 1 + wg;
      if (!wg) continue;
      wg_wait<0>();
      arrive_if(pb, prel);
      prel = 0;
    }
    bar_sync(1, 256);
  }
  wg_wait<0>();
  reg_fence_n<NA>(acc);
  if (MODE != 3) arrive_if(pb, prel & ~wg);
}

__device__ __forceinline__ float gelu_arg(float h) { return h * fmaf(8.0f * 0.044715f * 0.7978845608028654f, h * h, 2.0f * 0.7978845608028654f); }

__device__ __forceinline__ int kb2_order(int i) { const int wv = i / 6; return 6 * (i - 6 * wv) + ((0x431250 >> (4 * wv)) & 7); }

__device__ __forceinline__ void wait_flags(const unsigned* base, int n, int idx, unsigned target, uint64_t& ready) {
  if ((ready >> idx) & 1) return;
  const int l = threadIdx.x & 31;
  int it = 0;
  while (true) {
    unsigned a = ld_rlx(base + l), b = l + 32 < n ? ld_rlx(base + l + 32) : target;
    ready = (uint64_t)__ballot_sync(0xffffffffu, (int)(a - target) >= 0) | ((uint64_t)__ballot_sync(0xffffffffu, (int)(b - target) >= 0) << 32);
    if (((ready >> idx) & 1) || ++it > SPIN_MAX) break;
  }
  fence_async_glb();
}

enum { B_FULL = 0, B_EMPTY = 6, B_FLT = 12, B_Z1, B_Z2, B_GO, B_S4, B_S5, B_WM, B_NUM, B_W0 = B_NUM };

__global__ void __launch_bounds__(NTHR, 1)
fused_kernel(const Params p, const __grid_constant__ Maps maps) {
  extern __shared__ uint8_t smem_raw[];
  __shared__ uint64_t bars[B_NUM + 1];
  __shared__ __align__(16) float redbuf[128 + D_];

  const uint32_t sbase = (smem_u32(smem_raw) + 1023) & ~1023u;
  const uint32_t full0 = smem_u32(bars), empty0 = full0 + 8 * B_EMPTY, red = smem_u32(redbuf);
  const int tid = threadIdx.x, cta = blockIdx.x, t128 = tid & 127;
  const int wp = __shfl_sync(0xffffffffu, tid >> 5, 0), wg = wp >> 2;
  const int l = tid & 31, g = l >> 2, t = l & 3;
  Scratch* const sc = p.s;
  const bool rows = cta < 128;
  const int R = cta - 12;

  uint32_t xr[18];
  uint32_t cv[9];
  const unsigned ep = ld_rlx(&sc->cnt[C_EP]) + 1;
  if (tid == 0) TS(0);
  if (wg == 2) {
#pragma unroll
    for (int i = 0; i < 9; i++) asm volatile("ld.global.nc.u16 %0, [%1];" : "=r"(cv[i]) : "l"(p.c + (t128 >> 1) + 64 * i) : "memory");
    if (wp == 9 && l < 9 && rows) {
      const int h = 9 * cta + l;
      prefetch_l2(reinterpret_cast<const uint8_t*>(p.wmod) + (size_t)(h >> 1) * (12 * D_) + (h & 1) * (2 * D_), 2 * D_);
    }
    if (t128 < 16) {
#pragma unroll 1
      for (int u = cta < 72 ? cta : 72 + cta; u < 216; u += u < 72 ? 72 : NCTA) sc->mod[mod_pos(u, t128)] = 0;
    }
    if (tid == 256 && cta < 72) {
      mbar_init(full0 + 8 * B_W0, 1);
      fence_async_smem();
      mbar_expect(full0 + 8 * B_W0, 18432);
#pragma unroll 1
      for (int i = 0; i < 3; i++) tma2d(sbase + O_P2 + i * 6144, &maps.wm, 16 * cta, 192 * i, full0 + 8 * B_W0);
    }
    if (tid == 352) {
#pragma unroll 1
      for (int i = 0; i < B_NUM; i++) mbar_init(full0 + 8 * i, i == B_FLT ? 4 : i == B_WM ? 3 : (i >= B_EMPTY && i < B_FLT) || i == B_S4 || i == B_S5 ? 2 : 1);
      fence_async_smem();
    }
    if (wp == 10 && l < 12) asm volatile("prefetch.tensormap [%0];" ::"l"(&maps.w1a + l) : "memory");
    __syncwarp();
  }
  CK(0);
  auto load_x = [&]() {
    const uint32_t* xs = reinterpret_cast<const uint32_t*>(p.x) + (size_t)(cta + 256 * wp) * 288 + l;
#pragma unroll
    for (int i = 0; i < 9; i++) { xr[i] = ld_nc(xs + 32 * i); xr[9 + i] = ld_nc(xs + 128 * 288 + 32 * i); }
  };
  if (rows && wg < 2) load_x();
  if (tid == 64 && cta == NCTA - 1) prefetch_l2(p.tab, sizeof(T_TAB));
  __syncwarp();
  const uint32_t tag16 = (ep & 0x7fffu) | 0x8000u, tag1 = ep & 1u;

  if (wg == 2) {
    float sil[9];
#pragma unroll
    for (int i = 0; i < 9; i++) sil[i] = rbf(__fdividef(bf_lo(cv[i]), 1.0f + __expf(-bf_lo(cv[i]))));
    if (cta < 72) {
      float acc[8] = {0.f, 0.f, 0.f, 0.f, 0.f, 0.f, 0.f, 0.f};
      bar_sync(4, 128);
      mbar_wait(full0 + 8 * B_W0, 0);
      if (t128 == 0) TS(10);
#pragma unroll
      for (int i = 0; i < 9; i++) mod_fma(acc, sil[i], lds4(sbase + O_P2 + t128 * 16 + i * 2048));
      mod_finish(p, acc, cta, t128, red, tag16);
      if (t128 == 0) TS(25);
    }
#pragma unroll
    for (int i = 0; i < 9; i++) sts(red + 512 + ((t128 >> 1) + 64 * i) * 4, __float_as_uint(sil[i]));
    CK(1);
  }
  const int pi = R / 15, col0 = 20 * (R - 15 * pi);
  const int xu = DF_ * pi + col0, xv = DF_ * (pi ? 16 - pi : 8) + col0;
  auto load_filter = [&](int a) {
    const int x = (a & 1) ? xv : xu;
    const bool wide = (x & 15) > 12;
    mbar_expect(full0 + 8 * B_FLT, wide ? 12288 : 8192);
    tma2d(sbase + O_RAW + a * 12288, &maps.wf[a & 2], x & ~15, 0, full0 + 8 * B_FLT);
    if (wide) tma2d(sbase + O_RAW + a * 12288 + 8192, &maps.wf[(a & 2) + 1], (x & ~15) + 32, 0, full0 + 8 * B_FLT);
  };
  const int kap = 8 * ((wp & 3) ^ (wg & 1)) + g;
  uint4 af[4];
  if (rows) {
    uint32_t tb[4];
#pragma unroll
    for (int i = 0; i < 4; i++) tb[i] = pack_bf16(tmat(cta, 8 * (i >> 1) + g, 2 * t + 8 * (i & 1)), tmat(cta, 8 * (i >> 1) + g, 2 * t + 8 * (i & 1) + 1));
    uint32_t sb1[3], lo[9];
#pragma unroll
    for (int i = 0; i < 4; i++) tb[i] = pin(tb[i]);
#pragma unroll
    for (int i = 0; i < 3; i++) {
      const int d = 48 * wp + 16 * i + (l & 15);
      sb1[i] = pin(sbase + O_B1 + (l >> 4) * 9216 + (d % 9) * 1024 + (d & 63) * 16);
    }
    const uint32_t snt = pin(sbase + O_NRM + ((l & 7) + 8 * (l >> 4)) * 1168 + (48 * wp + (l & 8)) * 2);
    if (wg < 2) {
#pragma unroll
      for (int k1 = 0; k1 < 9; k1++) lo[k1] = pin(sbase + O_Z1 + line_off(k1, kap, 4 * wg + t, cta & 3));
#pragma unroll
      for (int kk = 0; kk < 4; kk++) af[kk] = __ldg(p.tab + TB_F + kk * 128 + (t128 ^ (wg << 5)));
      float a[18], b[18];
#pragma unroll
      for (int i = 0; i < 9; i++) { a[2 * i] = bf_lo(xr[i]); a[2 * i + 1] = bf_hi(xr[i]); b[2 * i] = bf_lo(xr[9 + i]); b[2 * i + 1] = bf_hi(xr[9 + i]); }
      float oa, ra, ob, rb;
      ln_stats2(a, b, 1.0f, oa, ra, ob, rb);
      CK(1);
      const uint32_t sn = sbase + O_NRM + wp * 2336 + l * 4;
#pragma unroll
      for (int i = 0; i < 9; i++) {
        sts(sn + i * 128, pack_bf16(fmaf(a[2 * i], ra, oa), fmaf(a[2 * i + 1], ra, oa)));
        sts(sn + 1168 + i * 128, pack_bf16(fmaf(b[2 * i], rb, ob), fmaf(b[2 * i + 1], rb, ob)));
      }
      CK(2);
      bar_arrive(10, NTHR);
      bar_sync(1, 256);
      if (tid == 0) TS(2);
    } else {
      bar_sync(10, NTHR);
      CK(2);
    }
    float rs[3][8];
#pragma unroll
    for (int i = 0; i < 3; i++) {
      uint32_t a0, a1, a2, a3;
      asm volatile("ldmatrix.sync.aligned.m8n8.x4.trans.shared.b16 {%0,%1,%2,%3}, [%4];" : "=r"(a0), "=r"(a1), "=r"(a2), "=r"(a3)
                   : "r"(snt + 32 * i) : "memory");
      mma16<false>(&rs[i][0], a0, a1, a2, a3, tb[0], tb[1]);
      mma16<false>(&rs[i][4], a0, a1, a2, a3, tb[2], tb[3]);
    }
    CK(3);
    {
      uint2 ms[3], mc[3];
      const uint32_t* mp = sc->mod + 48 * wp + 2 * g;
      int it = 0;
#pragma unroll 1
      while (true) {
        uint32_t bad = 0;
#pragma unroll
        for (int i = 0; i < 3; i++) { ms[i] = ld_rlx2(mp + 16 * i); mc[i] = ld_rlx2(mp + D_ + 16 * i); }
#pragma unroll
        for (int i = 0; i < 3; i++) {
          ms[i].x ^= tag16; ms[i].y ^= tag16; mc[i].x ^= tag16; mc[i].y ^= tag16;
          bad |= ms[i].x | ms[i].y | mc[i].x | mc[i].y;
        }
        if (!any(bad & 0xffffu) || ++it > SPIN_MAX) break;
      }
      CK(4);
      if (tid == 0) TS(3);
#pragma unroll
      for (int i = 0; i < 3; i++) {
        const float c0 = __uint_as_float(mc[i].x), c1 = __uint_as_float(mc[i].y);
        const float s0 = t ? 0.f : __uint_as_float(ms[i].x), s1 = t ? 0.f : __uint_as_float(ms[i].y);
        stmatrix4(sb1[i], pack_bf16(fmaf(rs[i][0], c0, s0), rs[i][1] * c0), pack_bf16(fmaf(rs[i][2], c1, s1), rs[i][3] * c1),
                  pack_bf16(rs[i][4] * c0, rs[i][5] * c0), pack_bf16(rs[i][6] * c1, rs[i][7] * c1));
      }
    }
    fence_async_smem();
    CK(5);
    if (wg == 2) {
      bar_arrive(5, NTHR);
      if (l == 0 && R >= 0) load_filter(wp - 8);
      __syncwarp();
    } else {
      bar_sync(5, NTHR);
      CK(6);
      float acc[36];
      const uint32_t db = (((sbase + O_B1 + wg * 9216) & 0x3FFFF) >> 4) | ((128 >> 4) << 16);
      wg_fence();
#pragma unroll
      for (int kk = 0; kk < 4; kk++) wgmma_rs_72(acc, af[kk].x, af[kk].y, af[kk].z, af[kk].w, db + kk * 16, 1024 >> 4, kk);
      wg_commit();
      wg_wait<0>();
      reg_fence(acc);
      CK(7);
      float2 za[9], zb[9];
#pragma unroll
      for (int i = 0; i < 9; i++) { za[i] = make_float2(acc[4 * i], acc[4 * i + 2]); zb[i] = make_float2(acc[4 * i + 1], acc[4 * i + 3]); }
      dft9(za); dft9(zb);
      if (kap == 0) {
#pragma unroll
        for (int k = 1; k < 5; k++) {
          float2 a = za[k], b = za[9 - k];
          za[k] = make_float2(a.x + b.x, a.y - b.y); za[9 - k] = make_float2(a.y + b.y, b.x - a.x);
          a = zb[k]; b = zb[9 - k];
          zb[k] = make_float2(a.x + b.x, a.y - b.y); zb[9 - k] = make_float2(a.y + b.y, b.x - a.x);
        }
        sts2(lo[0] + 288 * 8, set_tag(pack_bf16(za[0].y, 0.f), tag1), pack_bf16(zb[0].y, 0.f));
        za[0].y = 0.f; zb[0].y = 0.f;
      }
      __syncwarp();
#pragma unroll
      for (int k1 = 0; k1 < 9; k1++) sts2(lo[k1], set_tag(pack_bf16(za[k1].x, za[k1].y), tag1), pack_bf16(zb[k1].x, zb[k1].y));
      fence_async_smem();
      CK(8);
      bar_arrive(2 + wg, 160);
    }
  } else {
    __syncthreads();
  }

  if ((wp >> 1) == 4) {
    if (rows) bar_sync(wp - 6, 160);
    else { int it = 0; while (any((ld_rlx(sc->mod + 36 * l) ^ tag16) & 0xffffu) && ++it < SPIN_MAX) {} }
    if (l == 0) {
      const int slot = 4 * (cta & 7) + ((cta >> 4) & 3) + 32 * (2 * (cta >> 6) + ((cta >> 3) & 1));
      if (rows) {
        tma_st2d(&maps.z1, sbase + O_Z1 + (wp - 8) * 9600, 40 * slot, 60 * (wp - 8));
        HW();
        red_add(&sc->cnt[C_Z1 + 32 * (wp - 8)], 1);
        if (wp == 8) TS(4);
      } else { load_filter(wp - 8); load_filter(wp - 6); }
    }
    __syncwarp();
  }
  auto load_wm = [&](int u) {
    if (wp > 8 && l == 0) {
      mbar_expect(full0 + 8 * B_WM, 6144);
      tma2d(sbase + O_NRM + (wp - 9) * 6144, &maps.wm, 16 * u, 192 * (wp - 9), full0 + 8 * B_WM);
    }
    __syncwarp();
  };
  if (R >= 0) {
    const int ln0 = wg < 2 ? 2 * wp : 8 + wp;
    const int nl = min(wg < 2 ? 2 : 1, DF_ - col0 - ln0);
    uint4 cf[2][4], G[4];
#pragma unroll
    for (int i = 0; i < 4; i++) {
      cf[0][i] = __ldg(p.tab + TB_P2 + i * 32 + l);
      cf[1][i] = __ldg(p.tab + TB_P2 + (pi ? i : 4 + i) * 32 + l);
      G[i] = __ldg(p.tab + TB_P2 + (8 + i) * 32 + l);
    }
    const uint32_t* zin = sc->z1 + (size_t)R * 5120;
    if (wp == 10) {
      wait_cnt(&sc->cnt[C_Z1 + 32 * (pi >> 2)], 128 * ep);
      if (l == 0) {
        TS(12);
        mbar_expect(full0 + 8 * B_Z1, 20480);
        bulk_ld(sbase + O_P2, zin, 20480, full0 + 8 * B_Z1);
      }
      __syncwarp();
    }
    mbar_wait(full0 + 8 * B_FLT, 0);
    CK(9);
    float wn[16], wc[16];
#pragma unroll 1
    for (int ln = nl - 1; ln >= 0; ln--) {
      const int col = col0 + ln0 + ln, k2 = (57 * col) & 63;
      const bool cj = k2 > 32 || (k2 == 32 && col != 288);
      const float nr = ((col & 31) == 0 && col != 0 && col != 288 ? 0.5f : 1.0f) / ((float)S_ * D_), ni = cj ? -nr : nr;
#pragma unroll
      for (int i = 0; i < 16; i++) wn[i] = wc[i];
#pragma unroll
      for (int cl = 0; cl < 2; cl++) {
        const int v = cl ^ (cj && pi), e = ((v ? xv : xu) & 15) + ln0 + ln, sh = e < 32 ? 6 : 5;
        const uint32_t base = sbase + O_RAW + v * 12288 + (e < 32 ? 2 * e : 8192 - 64 + 2 * e), msk = e < 32 ? 0x30 : 0x10;
        const int dm = v ? (cj || pi ? -1 : 0) : 0;
#pragma unroll
        for (int tt = 0; tt < 4; tt++) {
          const int kc = g + 64 * (tt >> 1) + 16 * t + 8 * (tt & 1);
          uint32_t a = base + ((((cj ? -kc : kc) + dm) & 127) << sh);
          a ^= (a >> 3) & msk;
          wc[4 * tt + 2 * cl] = lds_bf(a) * nr; wc[4 * tt + 2 * cl + 1] = lds_bf(a + 24576) * ni;
        }
      }
    }
    const float al = pi ? 1.0f : 0.0f;
    CK(10);
    uint32_t off = pin(l * 160 + ((ln0 ^ (g & 3)) << 3));
    mbar_wait(full0 + 8 * B_Z1, 0);
    CK(11);
    if (tid == 0) TS(8);
    if (wg == 2) load_wm(72 + cta);
#pragma unroll 1
    for (int ln = 0; ln < nl; ln++, off ^= 8) {
      uint2 v[4];
#pragma unroll
      for (int i = 0; i < 4; i++) v[i] = lds2(sbase + O_P2 + off + i * 5120);
      if (__builtin_expect(any((diff2(v[0].x, v[1].x, tag1) | diff2(v[2].x, v[3].x, tag1)) & 1), 0)) {
        FAILCNT(0);
        int it = 0;
        do {
#pragma unroll
          for (int i = 0; i < 4; i++) v[i] = ld_rlx2(reinterpret_cast<const uint8_t*>(zin) + off + i * 5120);
        } while (any((diff2(v[0].x, v[1].x, tag1) | diff2(v[2].x, v[3].x, tag1)) & 1) && ++it < SPIN_MAX);
      }
      float d[4][4];
      uint32_t A[8];
#pragma unroll
      for (int h = 0; h < 2; h++) {
        mma16<false>(d[2 * h], cf[0][0].x, cf[0][0].y, cf[0][0].z, cf[0][0].w, v[h].x, v[2 + h].x);
        mma16<false>(d[2 * h + 1], cf[1][0].x, cf[1][0].y, cf[1][0].z, cf[1][0].w, v[h].y, v[2 + h].y);
      }
#pragma unroll
      for (int h = 0; h < 2; h++)
#pragma unroll
        for (int L = 0; L < 2; L++) {
          const uint4 tw = cf[L][2 + h];
          const float* z = d[2 * h + L];
          const float2 z0 = cmul(make_float2(z[0], z[2]), make_float2(__uint_as_float(tw.x), __uint_as_float(tw.y)));
          const float2 z1 = cmul(make_float2(z[1], z[3]), make_float2(__uint_as_float(tw.z), __uint_as_float(tw.w)));
          A[4 * h + L] = pack_bf16(z0.x, z0.y); A[4 * h + 2 + L] = pack_bf16(z1.x, z1.y);
        }
#pragma unroll
      for (int tt = 0; tt < 4; tt++) {
        mma16<false>(d[tt], A[0], A[1], A[2], A[3], G[tt].x, G[tt].y);
        mma16<true>(d[tt], A[4], A[5], A[6], A[7], G[tt].z, G[tt].w);
      }
#pragma unroll
      for (int tt = 0; tt < 4; tt++) {
        const float ar = d[tt][0], aj = d[tt][1], br = d[tt][2], bj = d[tt][3];
        const float2 y1 = cmul(make_float2(fmaf(-al, bj, ar), fmaf(al, br, aj)), make_float2(wc[4 * tt], wc[4 * tt + 1]));
        const float2 y2 = cmul(make_float2(fmaf(al, ar, bj), fmaf(al, aj, -br)), make_float2(wc[4 * tt + 2], wc[4 * tt + 3]));
        A[2 * tt] = pack_bf16(fmaf(al, y2.x, y1.x), fmaf(-al, y2.y, -y1.y));
        A[2 * tt + 1] = pack_bf16(fmaf(al, y1.y, -y2.y), fmaf(al, y1.x, -y2.x));
      }
#pragma unroll
      for (int i = 0; i < 16; i++) wc[i] = wn[i];
#pragma unroll
      for (int tt = 0; tt < 4; tt++) {
        mma16<false>(d[tt], A[0], A[1], A[2], A[3], G[tt].x, G[tt].y);
        mma16<true>(d[tt], A[4], A[5], A[6], A[7], G[tt].z, G[tt].w);
      }
#pragma unroll
      for (int h = 0; h < 2; h++)
#pragma unroll
        for (int L = 0; L < 2; L++) {
          const uint4 tw = cf[L][2 + h];
          const float2 z0 = cmul(make_float2(d[2 * h][2 * L], d[2 * h][2 * L + 1]), make_float2(__uint_as_float(tw.x), __uint_as_float(tw.y)));
          const float2 z1 = cmul(make_float2(d[2 * h + 1][2 * L], d[2 * h + 1][2 * L + 1]), make_float2(__uint_as_float(tw.z), __uint_as_float(tw.w)));
          A[4 * h + 2 * L] = movm(pack_bf16(z0.x, z1.x)); A[4 * h + 2 * L + 1] = movm(pack_bf16(z0.y, z1.y));
        }
#pragma unroll
      for (int h = 0; h < 2; h++) {
        mma16<false>(d[0], cf[0][1].x, cf[0][1].y, cf[0][1].z, cf[0][1].w, A[4 * h], A[4 * h + 1]);
        mma16<false>(d[1], cf[1][1].x, cf[1][1].y, cf[1][1].z, cf[1][1].w, A[4 * h + 2], A[4 * h + 3]);
#pragma unroll
        for (int e = 0; e < 2; e++)
          sts2(sbase + O_P2 + off + (2 * h + e) * 5120, set_tag(pack_bf16(d[0][e], d[0][2 + e]), tag1), pack_bf16(d[1][e], d[1][2 + e]));
      }
      CK(12 + ln);
    }
    fence_async_smem();
    if (wp) bar_arrive(6, NTHR);
    else {
      bar_sync(6, NTHR);
      if (l == 0) {
        tma_st2d(&maps.z2, sbase + O_P2, 40 * R, 0);
        HW();
        red_add(&sc->cnt[C_Z2], 1);
        TS(9);
      }
      __syncwarp();
    }
  }
  if (wg == 2) {
#pragma unroll 1
    for (int u = 72 + cta, k = 0; u < 216; u += NCTA, k ^= 1) {
      if (R < 0) { fence_async_smem(); bar_sync(4, 128); load_wm(u); }
      mbar_wait(full0 + 8 * B_WM, k);
      float acc[8] = {0.f, 0.f, 0.f, 0.f, 0.f, 0.f, 0.f, 0.f};
#pragma unroll 1
      for (int i = 0; i < 9; i++) mod_fma(acc, __uint_as_float(lds(red + 512 + ((t128 >> 1) + 64 * i) * 4)), lds4(sbase + O_NRM + t128 * 16 + i * 2048));
      mod_finish(p, acc, u, t128, red + 256 - 256 * k, tag16);
    }
    fence_async_smem();
    CK(13);
  }

  const int grp = cta / 11, m1 = cta - 11 * grp;
  const bool helper = (m1 & 3) == 3;
  const int f1 = 384 * grp + (helper ? 192 : 128) * (m1 >> 2);
  const int d1 = 160 * (m1 & 3), flip = m1 >= 7;
  const int a1bytes = helper ? 24576 : 16384;
  auto load_a1 = [&](int st, int kb) {
    mbar_expect(full0 + 8 * st, STAGE);
    tma4d_ef(sbase + st * STAGE, helper ? &maps.w1b : &maps.w1a, 4 * (kb >> 3), 16 * (kb & 7), f1 >> 6, full0 + 8 * st);
  };

  if (rows) {
#pragma unroll
    for (int kk = 0; kk < 4; kk++) af[kk] = __ldg(p.tab + TB_E + kk * 128 + t128);
    uint32_t tb[4], sy[6];
#pragma unroll
    for (int i = 0; i < 4; i++) tb[i] = pack_bf16(tmat(cta, 2 * t + 8 * (i & 1), 8 * (i >> 1) + g), tmat(cta, 2 * t + 8 * (i & 1) + 1, 8 * (i >> 1) + g));
#pragma unroll
    for (int i = 0; i < 6; i++) {
      const int rr = 16 * (wp & 3) + g + 8 * (i & 1);
      sy[i] = pin(sbase + O_Y + (t * 584 + 64 * ((3 * wg + (i >> 1) + 63 - rr) % 9) + rr) * 4);
    }
#pragma unroll
    for (int i = 0; i < 4; i++) tb[i] = pin(tb[i]);
    const int slot = 4 * (cta >> 4) + ((cta >> 1) & 3) + 32 * (2 * ((cta >> 3) & 1) + (cta & 1));
    const uint32_t* zin = sc->z2 + (size_t)slot * 4800;
    if (wg == 2) {
      {
        uint4 v[4];
        const int i3 = min(t128 + 384, 431);
        int it = 0;
        while (true) {
          uint32_t bad = 0;
#pragma unroll
          for (int k = 0; k < 4; k++) v[k] = ld_rlx4(sc->mod + 2 * D_ + 4 * (k < 3 ? t128 + 128 * k : i3));
#pragma unroll
          for (int k = 0; k < 4; k++) {
            v[k].x ^= tag16; v[k].y ^= tag16; v[k].z ^= tag16; v[k].w ^= tag16;
            bad |= v[k].x | v[k].y | v[k].z | v[k].w;
          }
          if (!any(bad & 0xffffu) || ++it > SPIN_MAX) break;
        }
#pragma unroll
        for (int k = 0; k < 4; k++) sts4(sbase + O_MOD + 16 * (k < 3 ? t128 + 128 * k : i3), v[k].x, v[k].y, v[k].z, v[k].w);
      }
      CK(14);
      mbar_wait(full0 + 8 * B_Z2, 0);
      if (l == 0) {
        load_a1(wp - 8, wp - 8);
        if (wp > 8 && wp - 8 < NG1) prefetch_l2(reinterpret_cast<const uint8_t*>(p.w1) + (size_t)(128 * (4 * ((wp - 8) >> 1) + (cta >> 5)) + 64 * (wp & 1) + 2 * (cta & 31)) * (2 * F_), 4 * F_);
      }
      __syncwarp();
    } else {
      uint32_t lo[9];
#pragma unroll
      for (int k1 = 0; k1 < 9; k1++) lo[k1] = pin(sbase + O_IN + line_off(k1, kap, 4 * wg + t, (cta >> 4) & 3));
      const uint32_t lx = pin(lo[0] + (kap ? 0 : 288 * 8));
      const uint32_t sb3 = pin(sbase + O_B3 + wg * 1024 + (l >> 4) * 2048 + (2 * (kap & 24) + (l & 15)) * 16);
      CK(14);
      if (wp == 0) {
        wait_cnt(&sc->cnt[C_Z2], 120 * ep);
        if (l == 0) {
          TS(14);
          mbar_expect(full0 + 8 * B_Z2, 19200);
          bulk_ld(sbase + O_IN, zin, 19200, full0 + 8 * B_Z2);
        }
        __syncwarp();
      }
      mbar_wait(full0 + 8 * B_Z2, 0);
      CK(15);
      if (tid == 0) TS(11);
      uint2 v[10];
      uint32_t bad = 0;
#pragma unroll
      for (int k1 = 0; k1 < 10; k1++) v[k1] = lds2(k1 < 9 ? lo[k1] : lx);
#pragma unroll
      for (int k1 = 0; k1 < 10; k1 += 2) bad |= diff2(v[k1].x, v[k1 + 1].x, tag1);
      if (__builtin_expect(any(bad & 1), 0)) {
        FAILCNT(1);
        int it = 0;
        do {
          bad = 0;
#pragma unroll
          for (int k1 = 0; k1 < 10; k1++) v[k1] = ld_rlx2(reinterpret_cast<const uint8_t*>(zin) + ((k1 < 9 ? lo[k1] : lx) - (sbase + O_IN)));
#pragma unroll
          for (int k1 = 0; k1 < 10; k1 += 2) bad |= diff2(v[k1].x, v[k1 + 1].x, tag1);
        } while (any(bad & 1) && ++it < SPIN_MAX);
      }
      float2 za[9], zb[9];
#pragma unroll
      for (int i = 0; i < 9; i++) { za[i] = make_float2(bf_lo(v[i].x), bf_hi(v[i].x)); zb[i] = make_float2(bf_lo(v[i].y), bf_hi(v[i].y)); }
      if (kap == 0) {
#pragma unroll
        for (int k = 1; k < 5; k++) {
          float2 a = za[k], b = za[9 - k];
          za[k] = make_float2(a.x - b.y, a.y + b.x); za[9 - k] = make_float2(a.x + b.y, b.x - a.y);
          a = zb[k]; b = zb[9 - k];
          zb[k] = make_float2(a.x - b.y, a.y + b.x); zb[9 - k] = make_float2(a.x + b.y, b.x - a.y);
        }
        za[0].y = bf_lo(v[9].x); zb[0].y = bf_lo(v[9].y);
      }
      __syncwarp();
      dft9(za); dft9(zb);
#pragma unroll
      for (int n = 0; n < 8; n += 2) {
        const int i0 = (9 - n) % 9, i1 = 8 - n;
        stmatrix4(sb3 + n * 2048, pack_bf16(za[i0].x, zb[i0].x), pack_bf16(za[i0].y, zb[i0].y), pack_bf16(za[i1].x, zb[i1].x), pack_bf16(za[i1].y, zb[i1].y));
      }
      stmatrix2(sb3 + 8 * 2048, pack_bf16(za[1].x, zb[1].x), pack_bf16(za[1].y, zb[1].y));
      fence_async_smem();
    }
    CK(16);
    __syncthreads();
    CK(17);
    float acc[24];
    const uint32_t db = (((sbase + O_B3 + wg * 6144) & 0x3FFFF) >> 4) | ((128 >> 4) << 16);
    wg_fence();
#pragma unroll
    for (int kk = 0; kk < 4; kk++) wgmma_rs_48(acc, af[kk].x, af[kk].y, af[kk].z, af[kk].w, db + kk * 16, 1024 >> 4, kk);
    wg_commit();
    uint32_t ga[9];
    uint2 sh[9], sw[9];
    if (wg < 2) {
#pragma unroll
      for (int i = 0; i < 9; i++) {
        const uint2 v = lds2(sbase + O_MOD + (64 * i + 2 * l) * 4);
        ga[i] = __byte_perm(v.x, v.y, 0x7632);
        sh[i] = lds2(sbase + O_MOD + (D_ + 64 * i + 2 * l) * 4);
        sw[i] = lds2(sbase + O_MOD + (2 * D_ + 64 * i + 2 * l) * 4);
      }
    }
    wg_wait<0>();
    reg_fence(acc);
    CK(18);
#pragma unroll
    for (int i = 0; i < 3; i++) {
      const float* a = &acc[8 * i];
      const uint32_t a0 = pack_bf16(a[0], a[1]), a1 = pack_bf16(a[2], a[3]), a2 = pack_bf16(a[4], a[5]), a3 = pack_bf16(a[6], a[7]);
#pragma unroll
      for (int jh = 0; jh < 2; jh++) {
        float y[4];
        mma16<false>(y, a0, a1, a2, a3, tb[2 * jh], tb[2 * jh + 1]);
        sts(sy[2 * i] + jh * (4 * 584 * 4), pack_bf16(y[0], y[1]));
        sts(sy[2 * i + 1] + jh * (4 * 584 * 4), pack_bf16(y[2], y[3]));
      }
    }
    CK(19);
    if (wg == 2) bar_arrive(7, NTHR);
    else {
      bar_sync(7, NTHR);
      CK(20);
      float a[18], b[18];
#pragma unroll
      for (int i = 0; i < 9; i++) {
        const uint2 y = lds2(sbase + O_Y + (wp * 584 + 64 * i + 2 * l) * 4);
        xr[i] = hfma2(ga[i], __byte_perm(y.x, y.y, 0x5410), xr[i]);
        xr[9 + i] = hfma2(ga[i], __byte_perm(y.x, y.y, 0x7632), xr[9 + i]);
        a[2 * i] = bf_lo(xr[i]); a[2 * i + 1] = bf_hi(xr[i]); b[2 * i] = bf_lo(xr[9 + i]); b[2 * i + 1] = bf_hi(xr[9 + i]);
      }
      float oa, ra, ob, rb;
      ln_stats2(a, b, 1.0f, oa, ra, ob, rb);
      CK(21);
#pragma unroll
      for (int i = 0; i < 9; i++) {
        const float c0 = __uint_as_float(sw[i].x), c1 = __uint_as_float(sw[i].y), s0 = __uint_as_float(sh[i].x), s1 = __uint_as_float(sh[i].y);
        a[2 * i] = fmaf(fmaf(a[2 * i], ra, oa), c0, s0); a[2 * i + 1] = fmaf(fmaf(a[2 * i + 1], ra, oa), c1, s1);
        b[2 * i] = fmaf(fmaf(b[2 * i], rb, ob), c0, s0); b[2 * i + 1] = fmaf(fmaf(b[2 * i + 1], rb, ob), c1, s1);
      }
      ln_stats2(a, b, 0.5f, oa, ra, ob, rb);
      CK(22);
      const uint32_t sh3 = sbase + O_B3 + (wp >> 1) * 4608 + (l >> 4) * 256 + (wp & 1) * 128 + ((((l >> 2) ^ (2 * cta + (wp & 1))) & 3) << 4) + (l & 3) * 4;
#pragma unroll
      for (int i = 0; i < 9; i++) {
        sts(sh3 + i * 512, pack_bf16(fmaf(a[2 * i], ra, oa), fmaf(a[2 * i + 1], ra, oa)));
        sts(sh3 + i * 512 + 64, pack_bf16(fmaf(b[2 * i], rb, ob), fmaf(b[2 * i + 1], rb, ob)));
      }
      fence_async_smem();
      if (wp == 0) CKX(0);
      bar_arrive(8 + wg, 160);
      CK(23);
    }
  } else __syncthreads();

  const bool g2 = cta < 130 && (cta >> 1) != 56;
  const int z2 = cta < 112 ? cta : cta - 2, r = z2 >> 6;
  const int s2 = 128 * ((z2 >> 2) & 15), d2 = 144 * (z2 & 3);
  constexpr int XST = (33 + 36 - JSK - 1) % NST;
  constexpr int ST0 = (32 - JSK - 1) % NST, ST1 = 31 % NST;

  if (wg == 2) {
    asm volatile("setmaxnreg.dec.sync.aligned.u32 40;");
    if (wp == 8) {
      int st = rows ? 4 : 0, ph = 1;
#pragma unroll 1
      for (int kb = st; kb < 32; kb++) {
        if (rows && (kb >> 1) == 2) mbar_wait(full0 + 8 * (B_S4 - 4 + kb), 0);
        mbar_wait(empty0 + 8 * st, ph);
        if (l == 0) {
          load_a1(st, kb);
          if (kb >= PF2K && kb < PF2K + PF2 && g2)
            prefetch_l2(reinterpret_cast<const uint8_t*>(p.w2) + (size_t)(36 * r + kb2_order(kb - PF2K)) * 262144 + (z2 & 63) * 4096, 4096);
        }
        __syncwarp();
        ring_next<false>(st, ph);
      }
      if (g2) {
        st++;
#pragma unroll 1
        for (int i = 0; i < 36; i++) {
          if (i == HOLDA) mbar_wait(full0 + 8 * B_GO, 0);
          mbar_wait(empty0 + 8 * st, ph);
          if (l == 0) {
            mbar_expect(full0 + 8 * st, 16384 + 18432);
            tma3d_ef(sbase + st * STAGE, &maps.w2, 64 * (36 * r + kb2_order(i)), s2 >> 6, full0 + 8 * st);
          }
          __syncwarp();
          ring_next<true>(st, ph);
        }
      }
    } else if (wp >= 10) {
      const int sw = wp - 10;
      if (rows) {
        bar_sync(8 + sw, 160);
        if (!sw) CKX(1);
        if (l == 0) mbar_arrive(full0 + 8 * B_S4);
        if (sw && H3W >= 0) { mbar_wait(full0 + 8 * H3W, 0); CKX(7); }
        if (l == 0) {
          tma_st3d(&maps.h3, sbase + O_B3 + sw * 9216, 64 * (cta & 15), 18 * (cta >> 4), 2 * sw);
          if (!sw) CKX(2);
          bulk_commit_wait();
          if (!sw) CKX(3);
          mbar_arrive(full0 + 8 * B_S5);
          asm volatile("fence.acq_rel.gpu;" ::: "memory");
          red_add(&sc->cnt[C_H3 + (cta >> 4) + 8 * sw], 1);
          if (!sw) CKX(4);
          TS(sw ? 24 : 13);
        }
        __syncwarp();
      }
      if (sw && g2) {
        mbar_wait(full0 + 8 * 5, 0);
#pragma unroll 1
        for (int i = 0; i < 36; i++) { sc->part[z2 * 1152 + 32 * i + l] = make_uint4(tag1 ^ 1, 0, 0, 0); __nanosleep(100); }
        __syncwarp();
      }
      const uint32_t stg = sbase + (sw ? ST1 : ST0) * STAGE;
      const int kbA = (f1 >> 6) + (helper ? 2 : 1) * (sw ^ flip), kbB = helper ? (f1 >> 6) + 1 : kbA;
      const int dB = helper ? d1 + 32 * sw : d1 + 96;
      bar_sync(11 + sw, 160);
      if (l == 0) { TS(sw ? 31 : 30); bulk_st(sc->u + ((size_t)kbA * D_ + d1) * 128, stg, 96 * 128); }
      __syncwarp();
      bar_sync(13 + sw, 160);
      if (l == 0) {
        bulk_st(sc->u + ((size_t)kbB * D_ + dB) * 128, stg + 96 * 128, helper ? 32 * 128 : 64 * 128);
        if (helper) bulk_st(sc->u + ((size_t)kbB * D_ + d1 + 64 + 16 * sw) * 128, stg + 128 * 128, 16 * 128);
        bulk_commit_wait();
        mbar_arrive(empty0 + 8 * (sw ? ST1 : ST0));
        if (sw == 0) TS(26);
        asm volatile("fence.acq_rel.gpu;" ::: "memory");
        red_add(&sc->cnt[C_U + kbA], 2);
        if (helper) red_add(&sc->cnt[C_U + kbB], 1);
        TS(sw ? 23 : 17);
      }
      __syncwarp();
    } else {
      uint64_t ready = 0;
      int st = 0, ph = 1;
#pragma unroll 1
      for (int kb = 0; kb < 32; kb++) {
        if (rows && (kb >> 1) == 2) mbar_wait(full0 + 8 * (B_S4 - 4 + kb), 0);
        mbar_wait(empty0 + 8 * st, ph);
        wait_flags(sc->cnt + C_H3, 32, (kb & 7) + ((kb >> 1) & 8), 16 * ep, ready);
        if (kb == 0) CKX(5);
        if (l == 0) bulk_ld(sbase + st * STAGE + a1bytes, sc->h3 + ((size_t)(kb * 18 + (d1 >> 5)) << 12), STAGE - a1bytes, full0 + 8 * st);
        if (kb == 0) CKX(6);
        if (kb == 5) CKX(8);
        if (kb == 16) CKX(9);
        ring_next<false>(st, ph);
      }
      if (g2) {
        ready = 0;
        st++;
#pragma unroll 1
        for (int i = 0; i < 72; i++) {
          if (i == 36) ready = 0;
          const int kb = kb2_order(i < 36 ? i : i - 36), hf = r ^ (i >= 36);
          if (i <= 36) mbar_wait(empty0 + 8 * st, ph);
          wait_flags(sc->cnt + C_U + 36 * hf, 36, kb, 8 * ep, ready);
          if (i < 36) {
            if (l == 0) {
              bulk_ld(sbase + st * STAGE + 16384, sc->u + ((size_t)(36 * r + kb) * D_ + d2) * 128, 18432, full0 + 8 * st);
              if (i == GOAT) mbar_arrive(full0 + 8 * B_GO);
            }
            ring_next<true>(st, ph);
          } else if (ready == ~0ull) break;
        }
        if (l == 0) mbar_expect(full0 + 8 * XST, 18432);
        __syncwarp();
        if (l < 3) tma2d(sbase + XST * STAGE + 18432 + l * 6144, &maps.x1, d2 + 48 * l, s2 + 64 * (r ^ 1), full0 + 8 * XST);
        __syncwarp();
      }
    }
  } else {
    asm volatile("setmaxnreg.inc.sync.aligned.u32 232;");
    const int wgu = wg;
    const uint32_t sb4 = sbase >> 4, fullu = full0;
    const int w = wp & 3;
    Ring rg = {0, 0};
    uint32_t* const x1p = sc->x1 + (size_t)(cta + 256 * wp) * 288 + l;
    float acc[80];
    constexpr uint32_t LA = (8192 >> 4) << 16, LB = (4096 >> 4) << 16;
    {
      const int fa = f1 + (helper ? 128 : 64) * (wg ^ flip) + 16 * w + g, fb = helper ? f1 + 64 + 16 * w + g : fa;
      const float a0 = 0.5f * __bfloat162float(p.b1[fa]), a1 = 0.5f * __bfloat162float(p.b1[fa + 8]);
      const float b0 = 0.5f * __bfloat162float(p.b1[fb]), b1 = 0.5f * __bfloat162float(p.b1[fb + 8]);
#pragma unroll
      for (int i = 0; i < 80; i++) acc[i] = i < 48 ? ((i & 2) ? a1 : a0) : ((i & 2) ? b1 : b0);
      reg_fence(acc);
    }
    if (!helper) gemm_main<0>(acc, sb4 + (wgu ^ flip) * 512 + LA, 0, sb4 + 1024 + LB, 0, wgu, rg, fullu, x1p, xr);
    else {
      float ac2[80];
#pragma unroll
      for (int i = 0; i < 72; i++) asm volatile("mov.b32 %0, %1;" : "=f"(ac2[i]) : "f"(acc[i]));
      gemm_main<1>(ac2, sb4 + (wgu ^ flip) * 1024 + LA, sb4 + 512 + LA, sb4 + 1536 + LB, sb4 + 1536 + (wgu ? 256 + LB + (2 << 16) : 2 * LB), wgu, rg, fullu, x1p, xr);
#pragma unroll
      for (int i = 0; i < 72; i++) asm volatile("mov.b32 %0, %1;" : "=f"(acc[i]) : "f"(ac2[i]));
    }
    if (t128 == 0) TS(wg ? 16 : 6);
    {
      const int mi = l >> 3, rr = l & 7;
      const uint32_t ad = sbase + (wg ? ST1 : ST0) * STAGE + (8 * (mi >> 1) + rr) * 128 + (((2 * w + (mi & 1)) ^ rr) << 4);
      float z[2][16];
#pragma unroll
      for (int j = -1; j <= 5; j++) {
        if (j >= 1) {
          const float* a = &acc[16 * (j - 1)];
          const float* tt = z[(j - 1) & 1];
#pragma unroll
          for (int h = 0; h < 16; h += 8)
            stmatrix4t(ad + (2 * (j - 1) + (h >> 3)) * 2048, pack_bf16(fmaf(a[h], tt[h], a[h]), fmaf(a[h + 1], tt[h + 1], a[h + 1])),
                       pack_bf16(fmaf(a[h + 2], tt[h + 2], a[h + 2]), fmaf(a[h + 3], tt[h + 3], a[h + 3])),
                       pack_bf16(fmaf(a[h + 4], tt[h + 4], a[h + 4]), fmaf(a[h + 5], tt[h + 5], a[h + 5])),
                       pack_bf16(fmaf(a[h + 6], tt[h + 6], a[h + 6]), fmaf(a[h + 7], tt[h + 7], a[h + 7])));
        }
        if (j >= 0 && j < 5) {
#pragma unroll
          for (int e = 0; e < 16; e++) asm("tanh.approx.f32 %0, %0;" : "+f"(z[j & 1][e]));
        }
        if (j < 4) {
#pragma unroll
          for (int e = 0; e < 16; e++) z[(j + 1) & 1][e] = gelu_arg(acc[16 * (j + 1) + e]);
        }
        if (j == 3 || j == 5) { fence_async_smem(); asm volatile("bar.arrive %0, 160;" ::"r"((j == 3 ? 11 : 13) + wgu) : "memory"); }
        if (j < 5) {
          if (j >= 0) reg_fence(z[j & 1]);
          if (j < 4) reg_fence(z[(j + 1) & 1]);
          if (__builtin_expect(sb4 == 0x7ffffff0u + j, 0)) __trap();
          reg_fence(acc);
        }
      }
      if (t128 == 0) TS(wg ? 29 : 28);
    }
    if (g2) {
      const int mb = wgu ^ r;
      uint32_t gb[18];
      {
        float a0 = 0.f, a1 = 0.f;
        if (wgu) {
          a0 = __bfloat162float(p.b2[s2 + 64 * mb + 16 * w + g]); a1 = __bfloat162float(p.b2[s2 + 64 * mb + 16 * w + 8 + g]);
          int it = 0;
          uint32_t bad;
          do {
            bad = 0;
#pragma unroll
            for (int i = 0; i < 18; i++) {
              const uint2 v = ld_rlx2(sc->mod + 5 * D_ + d2 + 8 * i + 2 * t);
              bad |= (v.x ^ tag16) | (v.y ^ tag16);
              gb[i] = __byte_perm(v.x, v.y, 0x7632);
            }
          } while (any(bad & 0xffffu) && ++it < SPIN_MAX);
        }
#pragma unroll
        for (int i = 0; i < 72; i++) acc[i] = (i & 2) ? a1 : a0;
      }
      rg.st++;
      gemm_main<3>(acc, sb4 + mb * 512 + LA, 0, sb4 + 1024 + (1 << 16), 0, wgu, rg, fullu, x1p, xr);
      if (t128 == 0) TS(wg ? 20 : 19);
      const uint32_t sx = sbase + XST * STAGE;
      if (wgu == 0) {
        uint4* dst = sc->part + z2 * 1152 + t128;
#pragma unroll
        for (int j = 0; j < 9; j++) {
          const float* a = &acc[8 * j];
          dst[j * 128] = make_uint4(set_tag(pack_bf16(a[0], a[1]), tag1), pack_bf16(a[2], a[3]), pack_bf16(a[4], a[5]), pack_bf16(a[6], a[7]));
        }
        if (tid == 0) TS(21);
        const uint4* src = sc->part + (z2 ^ 64) * 1152 + t128;
        uint4 v[9];
        uint32_t bad;
        int it = 0;
        do {
#pragma unroll
          for (int j = 0; j < 9; j++) v[j] = ld_rlx4(src + j * 128);
          bad = v[8].x ^ tag1;
#pragma unroll
          for (int j = 0; j < 8; j += 2) bad |= diff2(v[j].x, v[j + 1].x, tag1);
        } while (any(bad & 1) && ++it < SPIN_MAX);
#pragma unroll
        for (int j = 0; j < 9; j++) sts4(sx + t128 * 16 + j * 2048, v[j].x, v[j].y, v[j].z, v[j].w);
        bar_arrive(2 + w, 64);
        if (w == 0) {
#pragma unroll 1
          for (int i = 0; i < 3; i++) {
            bar_sync(11 + i, 160);
            if (l == 0) tma_st2d(&maps.out, sx + 18432 + i * 6144, d2 + 48 * i, s2 + 64 * (r ^ 1));
            __syncwarp();
          }
          if (l == 0) { bulk_commit_wait_read(); TS(22); }
          __syncwarp();
        }
      } else {
        mbar_wait(fullu + 8 * XST, rg.ph);
        bar_sync(2 + w, 64);
        if (t128 == 0) TS(5);
        if (tid == 128 && cta == 0) sc->cnt[C_EP] = ep;
        const uint32_t xa = sx + 18432 + (16 * w + (l & 15)) * 96 + (l >> 4) * 16;
#pragma unroll
        for (int c = 0; c < 3; c++) {
          uint32_t pv[3][4], xv[3][4];
#pragma unroll
          for (int j = 0; j < 3; j++) {
            asm volatile("ld.shared.v4.b32 {%0,%1,%2,%3}, [%4];" : "=r"(pv[j][0]), "=r"(pv[j][1]), "=r"(pv[j][2]), "=r"(pv[j][3]) : "r"(sx + t128 * 16 + (3 * c + j) * 2048) : "memory");
            asm volatile("ldmatrix.sync.aligned.m8n8.x4.shared.b16 {%0,%1,%2,%3}, [%4];" : "=r"(xv[j][0]), "=r"(xv[j][1]), "=r"(xv[j][2]), "=r"(xv[j][3]) : "r"(xa + c * 6144 + j * 32) : "memory");
          }
#pragma unroll
          for (int j = 0; j < 3; j++) {
            const float* a = &acc[8 * (3 * c + j)];
            uint32_t o[4];
#pragma unroll
            for (int e = 0; e < 4; e++)
              o[e] = hadd2(xv[j][e], hmul2(gb[2 * (3 * c + j) + (e >> 1)], pack_bf16(a[2 * e] + bf_lo(pv[j][e]), a[2 * e + 1] + bf_hi(pv[j][e]))));
            stmatrix4(xa + c * 6144 + j * 32, o[0], o[1], o[2], o[3]);
          }
          fence_async_smem();
          asm volatile("bar.arrive %0, 160;" ::"r"(11 + c) : "memory");
        }
        if (t128 == 0) TS(7);
        __syncwarp();
      }
    }
  }
}

typedef CUresult (*EncodeFn)(CUtensorMap*, CUtensorMapDataType, cuuint32_t, void*, const cuuint64_t*, const cuuint64_t*, const cuuint32_t*,
                             const cuuint32_t*, CUtensorMapInterleave, CUtensorMapSwizzle, CUtensorMapL2promotion, CUtensorMapFloatOOBfill);

struct Dim { cuuint64_t n, stride; cuuint32_t box; };
template <int RANK>
void make_map(EncodeFn enc, CUtensorMap* m, bool words, int swz, const void* ptr, const Dim (&d)[RANK]) {
  cuuint64_t gd[RANK], gs[RANK];
  cuuint32_t bx[RANK], es[RANK];
  for (int i = 0; i < RANK; i++) { gd[i] = d[i].n; gs[i] = d[i].stride; bx[i] = d[i].box; es[i] = 1; }
  enc(m, words ? CU_TENSOR_MAP_DATA_TYPE_UINT32 : CU_TENSOR_MAP_DATA_TYPE_BFLOAT16, RANK, const_cast<void*>(ptr), gd, gs + 1, bx, es,
      CU_TENSOR_MAP_INTERLEAVE_NONE, static_cast<CUtensorMapSwizzle>(swz),
      swz == 3 ? CU_TENSOR_MAP_L2_PROMOTION_L2_256B : CU_TENSOR_MAP_L2_PROMOTION_NONE, CU_TENSOR_MAP_FLOAT_OOB_FILL_NONE);
}

}

extern "C" void kernel_launch(void* const* d_in, const int* in_sizes, int n_in, void* d_out, int out_size) {
  (void)in_sizes; (void)n_in; (void)out_size;
  static EncodeFn enc = nullptr;
  static void *sptr = nullptr, *tptr = nullptr;
  if (!enc) {
    void* f = nullptr; cudaDriverEntryPointQueryResult qr;
    cudaGetDriverEntryPoint("cuTensorMapEncodeTiled", &f, cudaEnableDefault, &qr);
    enc = reinterpret_cast<EncodeFn>(f);
    cudaFuncSetAttribute(fused_kernel, cudaFuncAttributeMaxDynamicSharedMemorySize, SMEM_BYTES);
    cudaGetSymbolAddress(&sptr, g_s);
    cudaGetSymbolAddress(&tptr, T_TAB);
  }
  Params p;
  p.x = (const __nv_bfloat16*)d_in[0]; p.wr = (const __nv_bfloat16*)d_in[1]; p.wi = (const __nv_bfloat16*)d_in[2];
  p.b1 = (const __nv_bfloat16*)d_in[5]; p.b2 = (const __nv_bfloat16*)d_in[7];
  p.c = (const __nv_bfloat16*)d_in[8]; p.wmod = (const __nv_bfloat16*)d_in[9];
  p.w1 = (const __nv_bfloat16*)d_in[4]; p.w2 = (const __nv_bfloat16*)d_in[6];
  p.s = static_cast<Scratch*>(sptr); p.tab = static_cast<const uint4*>(tptr);
  Maps maps;
  make_map<4>(enc, &maps.w1a, false, 3, p.w1, {{64, 0, 64}, {16, 128 * 2 * F_, 4}, {128, 2 * F_, 16}, {72, 128, 2}});
  make_map<4>(enc, &maps.w1b, false, 3, p.w1, {{64, 0, 64}, {16, 128 * 2 * F_, 4}, {128, 2 * F_, 16}, {72, 128, 3}});
  make_map<3>(enc, &maps.w2, false, 3, p.w2, {{64, 0, 64}, {F_, 2 * S_, 64}, {32, 128, 2}});
  make_map<2>(enc, &maps.x1, false, 0, p.s->x1, {{D_, 0, 48}, {S_, 2 * D_, 64}});
  make_map<2>(enc, &maps.out, false, 0, d_out, {{D_, 0, 48}, {S_, 2 * D_, 64}});
  make_map<2>(enc, &maps.z1, true, 0, p.s->z1, {{5120, 0, 40}, {120, 20480, 60}});
  make_map<2>(enc, &maps.z2, true, 0, p.s->z2, {{4800, 0, 40}, {128, 19200, 128}});
  for (int i = 0; i < 4; i++) make_map<2>(enc, &maps.wf[i], false, 2 - (i & 1), (i & 2) ? p.wi : p.wr, {{16 * DF_, 0, (i & 1) ? 16u : 32u}, {128, 32 * DF_, 128}});
  make_map<2>(enc, &maps.wm, false, 0, p.wmod, {{6 * D_, 0, 16}, {D_, 12 * D_, 192}});
  make_map<3>(enc, &maps.h3, true, 0, p.s->h3, {{1024, 0, 64}, {144, 4096, 18}, {4, 144 * 4096, 2}});
  fused_kernel<<<NCTA, NTHR, SMEM_BYTES, cudaStreamPerThread>>>(p, maps);
}
```

```cpp
#include <cuda_runtime.h>
#include <cuda_bf16.h>
#include <cuda.h>
#include <stdint.h>

namespace {

constexpr int S_ = 2048, D_ = 576, DF_ = 289, F_ = 4608;
constexpr int NCTA = 132, NTHR = 384;
constexpr int STAGE = 36864, NST = 6;
constexpr uint32_t sbase = 1024, full0 = sbase + NST * STAGE, empty0 = full0 + 8 * NST, red = full0 + 256;
constexpr int SMEM_BYTES = NST * STAGE + 256 + 512 + 4 * D_ + 512;
constexpr int O_NRM = 0, O_B1 = 19456, O_Z1 = 38912, O_P2 = 59392;
constexpr int O_RAW = 4 * STAGE;
constexpr int O_IN = 4 * STAGE, O_Y = O_IN + 19456, O_B3 = O_IN + 38912, O_MOD = O_IN + 57344;

__device__ __align__(128) const uint32_t T_TAB[5632] = {
0x3f803f80,0xbf803f80,0x3f803f80,0xbf803f80,0x3f803f80,0xbf803f80,0x3f803f80,0xbf803f80,0x3f803f80,0xbf803f80,0x3f803f80,0xbf803f80,
0x3f803f80,0xbf803f80,0x3f803f80,0xbf803f80,0x3f7f3f80,0xbdc90000,0x3f223f35,0xbf46bf35,0x3f753f7b,0xbe95be48,0x3ef13f0e,0xbf62bf55,
0x3f623f6d,0xbef1bec4,0x3e953ec4,0xbf75bf6d,0x3f463f55,0xbf22bf0e,0x3dc93e48,0xbf7fbf7b,0x3f7b3f80,0xbe480000,0xbe480000,0xbf7bbf80,
0x3f553f6d,0xbf0ebec4,0xbf0ebec4,0xbf55bf6d,0x3f0e3f35,0xbf55bf35,0xbf55bf35,0xbf0ebf35,0x3e483ec4,0xbf7bbf6d,0xbf7bbf6d,0xbe48bec4,
0x3f753f80,0xbe950000,0xbf62bf35,0xbef1bf35,0x3f223f55,0xbf46bf0e,0xbf7fbf7b,0x3dc9be48,0x3dc93ec4,0xbf7fbf6d,0xbf46bf6d,0x3f223ec4,
0xbef1be48,0xbf62bf7b,0xbe95bf0e,0x3f753f55,0x3f6d3f80,0xbec40000,0xbf6dbf80,0x3ec40000,0x3ec43f35,0xbf6dbf35,0xbec4bf35,0x3f6d3f35,
0xbec40000,0xbf6dbf80,0x3ec40000,0x3f6d3f80,0xbf6dbf35,0xbec4bf35,0x3f6d3f35,0x3ec43f35,0x3f623f80,0xbef10000,0xbe95bf35,0x3f753f35,
0x3dc93f0e,0xbf7fbf55,0x3f223e48,0x3f463f7b,0xbf46bec4,0xbf22bf6d,0x3f7f3f6d,0xbdc93ec4,0xbf75bf7b,0x3e95be48,0x3ef13f55,0xbf62bf0e,
0x3f553f80,0xbf0e0000,0x3f0e0000,0x3f553f80,0xbe483ec4,0xbf7bbf6d,0x3f7b3f6d,0xbe483ec4,0xbf7bbf35,0xbe48bf35,0x3e483f35,0xbf7bbf35,
0xbf0ebf6d,0x3f553ec4,0xbf55bec4,0xbf0ebf6d,0x3f463f80,0xbf220000,0x3f7f3f35,0x3dc93f35,0xbef13e48,0xbf62bf7b,0x3e953f55,0xbf75bf0e,
0xbf75bf6d,0x3e95bec4,0xbf62bec4,0xbef1bf6d,0x3dc9bf0e,0x3f7f3f55,0xbf22bf7b,0x3f463e48,0x3f353f80,0xbf350000,0x3f353f80,0xbf350000,
0xbf350000,0xbf35bf80,0xbf350000,0xbf35bf80,0xbf35bf80,0x3f350000,0xbf35bf80,0x3f350000,0x3f350000,0x3f353f80,0x3f350000,0x3f353f80,
0x3f223f80,0xbf460000,0xbdc93f35,0xbf7fbf35,0xbf62be48,0xbef1bf7b,0xbf75bf55,0x3e95bf0e,0xbe95bf6d,0x3f753ec4,0x3ef1bec4,0x3f623f6d,
0x3f7f3f0e,0x3dc93f55,0x3f463f7b,0xbf223e48,0x3f0e3f80,0xbf550000,0xbf550000,0xbf0ebf80,0xbf7bbec4,0xbe48bf6d,0xbe48bf6d,0x3f7b3ec4,
0x3e48bf35,0x3f7b3f35,0x3f7b3f35,0xbe483f35,0x3f553f6d,0xbf0e3ec4,0xbf0e3ec4,0xbf55bf6d,0x3ef13f80,0xbf620000,0xbf75bf35,0x3e95bf35,
0xbf7fbf0e,0x3dc9bf55,0x3f46be48,0x3f223f7b,0x3f22bec4,0x3f463f6d,0x3dc93f6d,0xbf7fbec4,0x3e953f7b,0xbf75be48,0xbf62bf55,0x3ef1bf0e,
0x3ec43f80,0xbf6d0000,0xbec4bf80,0x3f6d0000,0xbf6dbf35,0x3ec4bf35,0x3f6d3f35,0xbec43f35,0x3f6d0000,0x3ec43f80,0xbf6d0000,0xbec4bf80,
0xbec43f35,0xbf6dbf35,0x3ec4bf35,0x3f6d3f35,0x3e953f80,0xbf750000,0x3ef1bf35,0x3f623f35,0xbf46bf55,0x3f22bf0e,0x3dc93f7b,0xbf7fbe48,
0x3f7f3ec4,0xbdc93f6d,0xbf22bf6d,0x3f46bec4,0xbf623e48,0xbef1bf7b,0x3f753f0e,0xbe953f55,0x3e483f80,0xbf7b0000,0x3f7b0000,0x3e483f80,
0xbf0ebf6d,0x3f55bec4,0xbf553ec4,0xbf0ebf6d,0x3f553f35,0xbf0e3f35,0x3f0ebf35,0x3f553f35,0xbf7bbec4,0x3e48bf6d,0xbe483f6d,0xbf7bbec4,
0x3dc93f80,0xbf7f0000,0x3f463f35,0xbf223f35,0xbe95bf7b,0x3f75be48,0xbf62bf0e,0x3ef1bf55,0x3ef13f6d,0xbf623ec4,0x3f753ec4,0xbe953f6d,
0xbf22bf55,0x3f46bf0e,0xbf7fbe48,0x3dc9bf7b,0x3f80,0xbf800000,0x3f80,0xbf800000,0xbf80,0x3f800000,0xbf80,0x3f800000,
0x3f80,0xbf800000,0x3f80,0xbf800000,0xbf80,0x3f800000,0xbf80,0x3f800000,0xbdc93f80,0xbf7f0000,0xbf463f35,0xbf22bf35,
0x3e95bf7b,0x3f753e48,0x3f62bf0e,0x3ef13f55,0xbef13f6d,0xbf62bec4,0xbf753ec4,0xbe95bf6d,0x3f22bf55,0x3f463f0e,0x3f7fbe48,0x3dc93f7b,
0xbe483f80,0xbf7b0000,0xbf7b0000,0x3e48bf80,0x3f0ebf6d,0x3f553ec4,0x3f553ec4,0xbf0e3f6d,0xbf553f35,0xbf0ebf35,0xbf0ebf35,0x3f55bf35,
0x3f7bbec4,0x3e483f6d,0x3e483f6d,0xbf7b3ec4,0xbe953f80,0xbf750000,0xbef1bf35,0x3f62bf35,0x3f46bf55,0x3f223f0e,0xbdc93f7b,0xbf7f3e48,
0xbf7f3ec4,0xbdc9bf6d,0x3f22bf6d,0x3f463ec4,0x3f623e48,0xbef13f7b,0xbf753f0e,0xbe95bf55,0xbec43f80,0xbf6d0000,0x3ec4bf80,0x3f6d0000,
0x3f6dbf35,0x3ec43f35,0xbf6d3f35,0xbec4bf35,0xbf6d0000,0x3ec4bf80,0x3f6d0000,0xbec43f80,0x3ec43f35,0xbf6d3f35,0xbec4bf35,0x3f6dbf35,
0xbef13f80,0xbf620000,0x3f75bf35,0x3e953f35,0x3f7fbf0e,0x3dc93f55,0xbf46be48,0x3f22bf7b,0xbf22bec4,0x3f46bf6d,0xbdc93f6d,0xbf7f3ec4,
0xbe953f7b,0xbf753e48,0x3f62bf55,0x3ef13f0e,0xbf0e3f80,0xbf550000,0x3f550000,0xbf0e3f80,0x3f7bbec4,0xbe483f6d,0x3e48bf6d,0x3f7bbec4,
0xbe48bf35,0x3f7bbf35,0xbf7b3f35,0xbe48bf35,0xbf553f6d,0xbf0ebec4,0x3f0e3ec4,0xbf553f6d,0xbf223f80,0xbf460000,0x3dc93f35,0xbf7f3f35,
0x3f62be48,0xbef13f7b,0x3f75bf55,0x3e953f0e,0x3e95bf6d,0x3f75bec4,0xbef1bec4,0x3f62bf6d,0xbf7f3f0e,0x3dc9bf55,0xbf463f7b,0xbf22be48,
0xbf353f80,0xbf350000,0xbf353f80,0xbf350000,0x3f350000,0xbf353f80,0x3f350000,0xbf353f80,0x3f35bf80,0x3f350000,0x3f35bf80,0x3f350000,
0xbf350000,0x3f35bf80,0xbf350000,0x3f35bf80,0xbf463f80,0xbf220000,0xbf7f3f35,0x3dc9bf35,0x3ef13e48,0xbf623f7b,0xbe953f55,0xbf753f0e,
0x3f75bf6d,0x3e953ec4,0x3f62bec4,0xbef13f6d,0xbdc9bf0e,0x3f7fbf55,0x3f22bf7b,0x3f46be48,0xbf553f80,0xbf0e0000,0xbf0e0000,0x3f55bf80,
0x3e483ec4,0xbf7b3f6d,0xbf7b3f6d,0xbe48bec4,0x3f7bbf35,0xbe483f35,0xbe483f35,0xbf7b3f35,0x3f0ebf6d,0x3f55bec4,0x3f55bec4,0xbf0e3f6d,
0xbf623f80,0xbef10000,0x3e95bf35,0x3f75bf35,0xbdc93f0e,0xbf7f3f55,0xbf223e48,0x3f46bf7b,0x3f46bec4,0xbf223f6d,0xbf7f3f6d,0xbdc9bec4,
0x3f75bf7b,0x3e953e48,0xbef13f55,0xbf623f0e,0xbf6d3f80,0xbec40000,0x3f6dbf80,0x3ec40000,0xbec43f35,0xbf6d3f35,0x3ec4bf35,0x3f6dbf35,
0x3ec40000,0xbf6d3f80,0xbec40000,0x3f6dbf80,0x3f6dbf35,0xbec43f35,0xbf6d3f35,0x3ec4bf35,0xbf753f80,0xbe950000,0x3f62bf35,0xbef13f35,
0xbf223f55,0xbf463f0e,0x3f7fbf7b,0x3dc93e48,0xbdc93ec4,0xbf7f3f6d,0x3f46bf6d,0x3f22bec4,0x3ef1be48,0xbf623f7b,0x3e95bf0e,0x3f75bf55,
0xbf7b3f80,0xbe480000,0x3e480000,0xbf7b3f80,0xbf553f6d,0xbf0e3ec4,0x3f0ebec4,0xbf553f6d,0xbf0e3f35,0xbf553f35,0x3f55bf35,0xbf0e3f35,
0xbe483ec4,0xbf7b3f6d,0x3f7bbf6d,0xbe483ec4,0xbf7f3f80,0xbdc90000,0xbf223f35,0xbf463f35,0xbf753f7b,0xbe953e48,0xbef13f0e,0xbf623f55,
0xbf623f6d,0xbef13ec4,0xbe953ec4,0xbf753f6d,0xbf463f55,0xbf223f0e,0xbdc93e48,0xbf7f3f7b,0x3f803f80,0xbf803f80,0x3f803f80,0xbf803f80,
0x3f803f80,0xbf803f80,0x3f803f80,0xbf803f80,0x3f803f80,0xbf803f80,0x3f803f80,0xbf803f80,0x3f803f80,0xbf803f80,0x3f803f80,0xbf803f80,
0xbdc90000,0xbf7fbf80,0xbf46bf35,0xbf22bf35,0xbe95be48,0xbf75bf7b,0xbf62bf55,0xbef1bf0e,0xbef1bec4,0xbf62bf6d,0xbf75bf6d,0xbe95bec4,
0xbf22bf0e,0xbf46bf55,0xbf7fbf7b,0xbdc9be48,0xbf7bbf80,0x3e480000,0x3e480000,0x3f7b3f80,0xbf55bf6d,0x3f0e3ec4,0x3f0e3ec4,0x3f553f6d,
0xbf0ebf35,0x3f553f35,0x3f553f35,0x3f0e3f35,0xbe48bec4,0x3f7b3f6d,0x3f7b3f6d,0x3e483ec4,0x3e950000,0x3f753f80,0x3ef13f35,0xbf62bf35,
0x3f463f0e,0x3f223f55,0xbdc93e48,0xbf7fbf7b,0x3f7f3f6d,0x3dc93ec4,0xbf22bec4,0xbf46bf6d,0x3f623f7b,0xbef1be48,0xbf75bf55,0xbe95bf0e,
0x3f6d3f80,0xbec40000,0xbf6dbf80,0x3ec40000,0x3ec43f35,0xbf6dbf35,0xbec4bf35,0x3f6d3f35,0xbec40000,0xbf6dbf80,0x3ec40000,0x3f6d3f80,
0xbf6dbf35,0xbec4bf35,0x3f6d3f35,0x3ec43f35,0xbef10000,0xbf62bf80,0x3f753f35,0x3e953f35,0xbf7fbf55,0xbdc9bf0e,0x3f463f7b,0xbf22be48,
0xbf22bf6d,0x3f463ec4,0xbdc93ec4,0xbf7fbf6d,0x3e95be48,0x3f753f7b,0xbf62bf0e,0xbef1bf55,0xbf55bf80,0x3f0e0000,0xbf0e0000,0xbf55bf80,
0x3e48bec4,0x3f7b3f6d,0xbf7bbf6d,0x3e48bec4,0x3f7b3f35,0x3e483f35,0xbe48bf35,0x3f7b3f35,0x3f0e3f6d,0xbf55bec4,0x3f553ec4,0x3f0e3f6d,
0x3f220000,0x3f463f80,0xbdc9bf35,0x3f7f3f35,0x3f623f7b,0xbef13e48,0x3f753f0e,0x3e953f55,0xbe953ec4,0xbf75bf6d,0x3ef13f6d,0xbf62bec4,
0xbf7fbf55,0x3dc9bf0e,0xbf46be48,0xbf22bf7b,0x3f353f80,0xbf350000,0x3f353f80,0xbf350000,0xbf350000,0xbf35bf80,0xbf350000,0xbf35bf80,
0xbf35bf80,0x3f350000,0xbf35bf80,0x3f350000,0x3f350000,0x3f353f80,0x3f350000,0x3f353f80,0xbf460000,0xbf22bf80,0xbf7fbf35,0x3dc9bf35,
0xbef1bf7b,0x3f623e48,0x3e95bf0e,0x3f753f55,0x3f753ec4,0x3e953f6d,0x3f623f6d,0xbef13ec4,0x3dc93f55,0xbf7fbf0e,0xbf223e48,0xbf46bf7b,
0xbf0ebf80,0x3f550000,0x3f550000,0x3f0e3f80,0x3f7b3ec4,0x3e483f6d,0x3e483f6d,0xbf7bbec4,0xbe483f35,0xbf7bbf35,0xbf7bbf35,0x3e48bf35,
0xbf55bf6d,0x3f0ebec4,0x3f0ebec4,0x3f553f6d,0x3f620000,0x3ef13f80,0xbe953f35,0xbf75bf35,0xbdc93f55,0xbf7fbf0e,0xbf22bf7b,0x3f46be48,
0xbf46bf6d,0x3f22bec4,0x3f7f3ec4,0x3dc93f6d,0x3f753e48,0x3e953f7b,0xbef13f0e,0xbf62bf55,0x3ec43f80,0xbf6d0000,0xbec4bf80,0x3f6d0000,
0xbf6dbf35,0x3ec4bf35,0x3f6d3f35,0xbec43f35,0x3f6d0000,0x3ec43f80,0xbf6d0000,0xbec4bf80,0xbec43f35,0xbf6dbf35,0x3ec4bf35,0x3f6d3f35,
0xbf750000,0xbe95bf80,0x3f623f35,0xbef13f35,0x3f22bf0e,0x3f463f55,0xbf7fbe48,0xbdc9bf7b,0xbdc93f6d,0xbf7fbec4,0x3f46bec4,0x3f223f6d,
0xbef1bf7b,0x3f62be48,0xbe953f55,0xbf75bf0e,0xbe48bf80,0x3f7b0000,0xbf7b0000,0xbe48bf80,0x3f0e3f6d,0xbf553ec4,0x3f55bec4,0x3f0e3f6d,
0xbf55bf35,0x3f0ebf35,0xbf0e3f35,0xbf55bf35,0x3f7b3ec4,0xbe483f6d,0x3e48bf6d,0x3f7b3ec4,0x3f7f0000,0x3dc93f80,0x3f22bf35,0x3f463f35,
0xbf753e48,0xbe95bf7b,0xbef13f55,0xbf62bf0e,0x3f62bec4,0x3ef13f6d,0x3e95bf6d,0x3f753ec4,0xbf463f0e,0xbf22bf55,0xbdc93f7b,0xbf7fbe48,
0x3f80,0xbf800000,0x3f80,0xbf800000,0xbf80,0x3f800000,0xbf80,0x3f800000,0x3f80,0xbf800000,0x3f80,0xbf800000,
0xbf80,0x3f800000,0xbf80,0x3f800000,0xbf7f0000,0x3dc9bf80,0xbf22bf35,0x3f46bf35,0x3f753e48,0xbe953f7b,0x3ef13f55,0xbf623f0e,
0xbf62bec4,0x3ef1bf6d,0xbe95bf6d,0x3f75bec4,0x3f463f0e,0xbf223f55,0x3dc93f7b,0xbf7f3e48,0x3e48bf80,0x3f7b0000,0x3f7b0000,0xbe483f80,
0xbf0e3f6d,0xbf55bec4,0xbf55bec4,0x3f0ebf6d,0x3f55bf35,0x3f0e3f35,0x3f0e3f35,0xbf553f35,0xbf7b3ec4,0xbe48bf6d,0xbe48bf6d,0x3f7bbec4,
0x3f750000,0xbe953f80,0xbf623f35,0xbef1bf35,0xbf22bf0e,0x3f46bf55,0x3f7fbe48,0xbdc93f7b,0x3dc93f6d,0xbf7f3ec4,0xbf46bec4,0x3f22bf6d,
0x3ef1bf7b,0x3f623e48,0x3e953f55,0xbf753f0e,0xbec43f80,0xbf6d0000,0x3ec4bf80,0x3f6d0000,0x3f6dbf35,0x3ec43f35,0xbf6d3f35,0xbec4bf35,
0xbf6d0000,0x3ec4bf80,0x3f6d0000,0xbec43f80,0x3ec43f35,0xbf6d3f35,0xbec4bf35,0x3f6dbf35,0xbf620000,0x3ef1bf80,0x3e953f35,0xbf753f35,
0x3dc93f55,0xbf7f3f0e,0x3f22bf7b,0x3f463e48,0x3f46bf6d,0x3f223ec4,0xbf7f3ec4,0x3dc9bf6d,0xbf753e48,0x3e95bf7b,0x3ef13f0e,0xbf623f55,
0x3f0ebf80,0x3f550000,0xbf550000,0x3f0ebf80,0xbf7b3ec4,0x3e48bf6d,0xbe483f6d,0xbf7b3ec4,0x3e483f35,0xbf7b3f35,0x3f7bbf35,0x3e483f35,
0x3f55bf6d,0x3f0e3ec4,0xbf0ebec4,0x3f55bf6d,0x3f460000,0xbf223f80,0x3f7fbf35,0x3dc93f35,0x3ef1bf7b,0x3f62be48,0xbe95bf0e,0x3f75bf55,
0xbf753ec4,0x3e95bf6d,0xbf623f6d,0xbef1bec4,0xbdc93f55,0xbf7f3f0e,0x3f223e48,0xbf463f7b,0xbf353f80,0xbf350000,0xbf353f80,0xbf350000,
0x3f350000,0xbf353f80,0x3f350000,0xbf353f80,0x3f35bf80,0x3f350000,0x3f35bf80,0x3f350000,0xbf350000,0x3f35bf80,0xbf350000,0x3f35bf80,
0xbf220000,0x3f46bf80,0x3dc9bf35,0x3f7fbf35,0xbf623f7b,0xbef1be48,0xbf753f0e,0x3e95bf55,0x3e953ec4,0xbf753f6d,0xbef13f6d,0xbf623ec4,
0x3f7fbf55,0x3dc93f0e,0x3f46be48,0xbf223f7b,0x3f55bf80,0x3f0e0000,0x3f0e0000,0xbf553f80,0xbe48bec4,0x3f7bbf6d,0x3f7bbf6d,0x3e483ec4,
0xbf7b3f35,0x3e48bf35,0x3e48bf35,0x3f7bbf35,0xbf0e3f6d,0xbf553ec4,0xbf553ec4,0x3f0ebf6d,0x3ef10000,0xbf623f80,0xbf753f35,0x3e95bf35,
0x3f7fbf55,0xbdc93f0e,0xbf463f7b,0xbf223e48,0x3f22bf6d,0x3f46bec4,0x3dc93ec4,0xbf7f3f6d,0xbe95be48,0x3f75bf7b,0x3f62bf0e,0xbef13f55,
0xbf6d3f80,0xbec40000,0x3f6dbf80,0x3ec40000,0xbec43f35,0xbf6d3f35,0x3ec4bf35,0x3f6dbf35,0x3ec40000,0xbf6d3f80,0xbec40000,0x3f6dbf80,
0x3f6dbf35,0xbec43f35,0xbf6d3f35,0x3ec4bf35,0xbe950000,0x3f75bf80,0xbef13f35,0xbf623f35,0xbf463f0e,0x3f22bf55,0x3dc93e48,0xbf7f3f7b,
0xbf7f3f6d,0x3dc9bec4,0x3f22bec4,0xbf463f6d,0xbf623f7b,0xbef13e48,0x3f75bf55,0xbe953f0e,0x3f7bbf80,0x3e480000,0xbe480000,0x3f7bbf80,
0x3f55bf6d,0x3f0ebec4,0xbf0e3ec4,0x3f55bf6d,0x3f0ebf35,0x3f55bf35,0xbf553f35,0x3f0ebf35,0x3e48bec4,0x3f7bbf6d,0xbf7b3f6d,0x3e48bec4,
0x3dc90000,0xbf7f3f80,0x3f46bf35,0xbf223f35,0x3e95be48,0xbf753f7b,0x3f62bf55,0xbef13f0e,0x3ef1bec4,0xbf623f6d,0x3f75bf6d,0xbe953ec4,
0x3f22bf0e,0xbf463f55,0x3f7fbf7b,0xbdc93e48,0x3f803f80,0xbf803f80,0x3f803f80,0xbf803f80,0x3f803f80,0xbf803f80,0x3f803f80,0xbf803f80,
0x3f803f80,0xbf803f80,0x3f803f80,0xbf803f80,0x3f803f80,0xbf803f80,0x3f803f80,0xbf803f80,0xbf7fbf80,0x3dc90000,0xbf22bf35,0x3f463f35,
0xbf75bf7b,0x3e953e48,0xbef1bf0e,0x3f623f55,0xbf62bf6d,0x3ef13ec4,0xbe95bec4,0x3f753f6d,0xbf46bf55,0x3f223f0e,0xbdc9be48,0x3f7f3f7b,
0x3f7b3f80,0xbe480000,0xbe480000,0xbf7bbf80,0x3f553f6d,0xbf0ebec4,0xbf0ebec4,0xbf55bf6d,0x3f0e3f35,0xbf55bf35,0xbf55bf35,0xbf0ebf35,
0x3e483ec4,0xbf7bbf6d,0xbf7bbf6d,0xbe48bec4,0xbf75bf80,0x3e950000,0x3f623f35,0x3ef13f35,0xbf22bf55,0x3f463f0e,0x3f7f3f7b,0xbdc93e48,
0xbdc9bec4,0x3f7f3f6d,0x3f463f6d,0xbf22bec4,0x3ef13e48,0x3f623f7b,0x3e953f0e,0xbf75bf55,0x3f6d3f80,0xbec40000,0xbf6dbf80,0x3ec40000,
0x3ec43f35,0xbf6dbf35,0xbec4bf35,0x3f6d3f35,0xbec40000,0xbf6dbf80,0x3ec40000,0x3f6d3f80,0xbf6dbf35,0xbec4bf35,0x3f6d3f35,0x3ec43f35,
0xbf62bf80,0x3ef10000,0x3e953f35,0xbf75bf35,0xbdc9bf0e,0x3f7f3f55,0xbf22be48,0xbf46bf7b,0x3f463ec4,0x3f223f6d,0xbf7fbf6d,0x3dc9bec4,
0x3f753f7b,0xbe953e48,0xbef1bf55,0x3f623f0e,0x3f553f80,0xbf0e0000,0x3f0e0000,0x3f553f80,0xbe483ec4,0xbf7bbf6d,0x3f7b3f6d,0xbe483ec4,
0xbf7bbf35,0xbe48bf35,0x3e483f35,0xbf7bbf35,0xbf0ebf6d,0x3f553ec4,0xbf55bec4,0xbf0ebf6d,0xbf46bf80,0x3f220000,0xbf7fbf35,0xbdc9bf35,
0x3ef1be48,0x3f623f7b,0xbe95bf55,0x3f753f0e,0x3f753f6d,0xbe953ec4,0x3f623ec4,0x3ef13f6d,0xbdc93f0e,0xbf7fbf55,0x3f223f7b,0xbf46be48,
0x3f353f80,0xbf350000,0x3f353f80,0xbf350000,0xbf350000,0xbf35bf80,0xbf350000,0xbf35bf80,0xbf35bf80,0x3f350000,0xbf35bf80,0x3f350000,
0x3f350000,0x3f353f80,0x3f350000,0x3f353f80,0xbf22bf80,0x3f460000,0x3dc9bf35,0x3f7f3f35,0x3f623e48,0x3ef13f7b,0x3f753f55,0xbe953f0e,
0x3e953f6d,0xbf75bec4,0xbef13ec4,0xbf62bf6d,0xbf7fbf0e,0xbdc9bf55,0xbf46bf7b,0x3f22be48,0x3f0e3f80,0xbf550000,0xbf550000,0xbf0ebf80,
0xbf7bbec4,0xbe48bf6d,0xbe48bf6d,0x3f7b3ec4,0x3e48bf35,0x3f7b3f35,0x3f7b3f35,0xbe483f35,0x3f553f6d,0xbf0e3ec4,0xbf0e3ec4,0xbf55bf6d,
0xbef1bf80,0x3f620000,0x3f753f35,0xbe953f35,0x3f7f3f0e,0xbdc93f55,0xbf463e48,0xbf22bf7b,0xbf223ec4,0xbf46bf6d,0xbdc9bf6d,0x3f7f3ec4,
0xbe95bf7b,0x3f753e48,0x3f623f55,0xbef13f0e,0x3ec43f80,0xbf6d0000,0xbec4bf80,0x3f6d0000,0xbf6dbf35,0x3ec4bf35,0x3f6d3f35,0xbec43f35,
0x3f6d0000,0x3ec43f80,0xbf6d0000,0xbec4bf80,0xbec43f35,0xbf6dbf35,0x3ec4bf35,0x3f6d3f35,0xbe95bf80,0x3f750000,0xbef13f35,0xbf62bf35,
0x3f463f55,0xbf223f0e,0xbdc9bf7b,0x3f7f3e48,0xbf7fbec4,0x3dc9bf6d,0x3f223f6d,0xbf463ec4,0x3f62be48,0x3ef13f7b,0xbf75bf0e,0x3e95bf55,
0x3e483f80,0xbf7b0000,0x3f7b0000,0x3e483f80,0xbf0ebf6d,0x3f55bec4,0xbf553ec4,0xbf0ebf6d,0x3f553f35,0xbf0e3f35,0x3f0ebf35,0x3f553f35,
0xbf7bbec4,0x3e48bf6d,0xbe483f6d,0xbf7bbec4,0xbdc9bf80,0x3f7f0000,0xbf46bf35,0x3f22bf35,0x3e953f7b,0xbf753e48,0x3f623f0e,0xbef13f55,
0xbef1bf6d,0x3f62bec4,0xbf75bec4,0x3e95bf6d,0x3f223f55,0xbf463f0e,0x3f7f3e48,0xbdc93f7b,0x3f80,0xbf800000,0x3f80,0xbf800000,
0xbf80,0x3f800000,0xbf80,0x3f800000,0x3f80,0xbf800000,0x3f80,0xbf800000,0xbf80,0x3f800000,0xbf80,0x3f800000,
0x3dc9bf80,0x3f7f0000,0x3f46bf35,0x3f223f35,0xbe953f7b,0xbf75be48,0xbf623f0e,0xbef1bf55,0x3ef1bf6d,0x3f623ec4,0x3f75bec4,0x3e953f6d,
0xbf223f55,0xbf46bf0e,0xbf7f3e48,0xbdc9bf7b,0xbe483f80,0xbf7b0000,0xbf7b0000,0x3e48bf80,0x3f0ebf6d,0x3f553ec4,0x3f553ec4,0xbf0e3f6d,
0xbf553f35,0xbf0ebf35,0xbf0ebf35,0x3f55bf35,0x3f7bbec4,0x3e483f6d,0x3e483f6d,0xbf7b3ec4,0x3e95bf80,0x3f750000,0x3ef13f35,0xbf623f35,
0xbf463f55,0xbf22bf0e,0x3dc9bf7b,0x3f7fbe48,0x3f7fbec4,0x3dc93f6d,0xbf223f6d,0xbf46bec4,0xbf62be48,0x3ef1bf7b,0x3f75bf0e,0x3e953f55,
0xbec43f80,0xbf6d0000,0x3ec4bf80,0x3f6d0000,0x3f6dbf35,0x3ec43f35,0xbf6d3f35,0xbec4bf35,0xbf6d0000,0x3ec4bf80,0x3f6d0000,0xbec43f80,
0x3ec43f35,0xbf6d3f35,0xbec4bf35,0x3f6dbf35,0x3ef1bf80,0x3f620000,0xbf753f35,0xbe95bf35,0xbf7f3f0e,0xbdc9bf55,0x3f463e48,0xbf223f7b,
0x3f223ec4,0xbf463f6d,0x3dc9bf6d,0x3f7fbec4,0x3e95bf7b,0x3f75be48,0xbf623f55,0xbef1bf0e,0xbf0e3f80,0xbf550000,0x3f550000,0xbf0e3f80,
0x3f7bbec4,0xbe483f6d,0x3e48bf6d,0x3f7bbec4,0xbe48bf35,0x3f7bbf35,0xbf7b3f35,0xbe48bf35,0xbf553f6d,0xbf0ebec4,0x3f0e3ec4,0xbf553f6d,
0x3f22bf80,0x3f460000,0xbdc9bf35,0x3f7fbf35,0xbf623e48,0x3ef1bf7b,0xbf753f55,0xbe95bf0e,0xbe953f6d,0xbf753ec4,0x3ef13ec4,0xbf623f6d,
0x3f7fbf0e,0xbdc93f55,0x3f46bf7b,0x3f223e48,0xbf353f80,0xbf350000,0xbf353f80,0xbf350000,0x3f350000,0xbf353f80,0x3f350000,0xbf353f80,
0x3f35bf80,0x3f350000,0x3f35bf80,0x3f350000,0xbf350000,0x3f35bf80,0xbf350000,0x3f35bf80,0x3f46bf80,0x3f220000,0x3f7fbf35,0xbdc93f35,
0xbef1be48,0x3f62bf7b,0x3e95bf55,0x3f75bf0e,0xbf753f6d,0xbe95bec4,0xbf623ec4,0x3ef1bf6d,0x3dc93f0e,0xbf7f3f55,0xbf223f7b,0xbf463e48,
0xbf553f80,0xbf0e0000,0xbf0e0000,0x3f55bf80,0x3e483ec4,0xbf7b3f6d,0xbf7b3f6d,0xbe48bec4,0x3f7bbf35,0xbe483f35,0xbe483f35,0xbf7b3f35,
0x3f0ebf6d,0x3f55bec4,0x3f55bec4,0xbf0e3f6d,0x3f62bf80,0x3ef10000,0xbe953f35,0xbf753f35,0x3dc9bf0e,0x3f7fbf55,0x3f22be48,0xbf463f7b,
0xbf463ec4,0x3f22bf6d,0x3f7fbf6d,0x3dc93ec4,0xbf753f7b,0xbe95be48,0x3ef1bf55,0x3f62bf0e,0xbf6d3f80,0xbec40000,0x3f6dbf80,0x3ec40000,
0xbec43f35,0xbf6d3f35,0x3ec4bf35,0x3f6dbf35,0x3ec40000,0xbf6d3f80,0xbec40000,0x3f6dbf80,0x3f6dbf35,0xbec43f35,0xbf6d3f35,0x3ec4bf35,
0x3f75bf80,0x3e950000,0xbf623f35,0x3ef1bf35,0x3f22bf55,0x3f46bf0e,0xbf7f3f7b,0xbdc9be48,0x3dc9bec4,0x3f7fbf6d,0xbf463f6d,0xbf223ec4,
0xbef13e48,0x3f62bf7b,0xbe953f0e,0xbf753f55,0xbf7b3f80,0xbe480000,0x3e480000,0xbf7b3f80,0xbf553f6d,0xbf0e3ec4,0x3f0ebec4,0xbf553f6d,
0xbf0e3f35,0xbf553f35,0x3f55bf35,0xbf0e3f35,0xbe483ec4,0xbf7b3f6d,0x3f7bbf6d,0xbe483ec4,0x3f7fbf80,0x3dc90000,0x3f22bf35,0x3f46bf35,
0x3f75bf7b,0x3e95be48,0x3ef1bf0e,0x3f62bf55,0x3f62bf6d,0x3ef1bec4,0x3e95bec4,0x3f75bf6d,0x3f46bf55,0x3f22bf0e,0x3dc9be48,0x3f7fbf7b,
0x3f803f80,0xbf803f80,0x3f803f80,0xbf803f80,0x3f803f80,0xbf803f80,0x3f803f80,0xbf803f80,0x3f803f80,0xbf803f80,0x3f803f80,0xbf803f80,
0x3f803f80,0xbf803f80,0x3f803f80,0xbf803f80,0x3dc90000,0x3f7f3f80,0x3f463f35,0x3f223f35,0x3e953e48,0x3f753f7b,0x3f623f55,0x3ef13f0e,
0x3ef13ec4,0x3f623f6d,0x3f753f6d,0x3e953ec4,0x3f223f0e,0x3f463f55,0x3f7f3f7b,0x3dc93e48,0xbf7bbf80,0x3e480000,0x3e480000,0x3f7b3f80,
0xbf55bf6d,0x3f0e3ec4,0x3f0e3ec4,0x3f553f6d,0xbf0ebf35,0x3f553f35,0x3f553f35,0x3f0e3f35,0xbe48bec4,0x3f7b3f6d,0x3f7b3f6d,0x3e483ec4,
0xbe950000,0xbf75bf80,0xbef1bf35,0x3f623f35,0xbf46bf0e,0xbf22bf55,0x3dc9be48,0x3f7f3f7b,0xbf7fbf6d,0xbdc9bec4,0x3f223ec4,0x3f463f6d,
0xbf62bf7b,0x3ef13e48,0x3f753f55,0x3e953f0e,0x3f6d3f80,0xbec40000,0xbf6dbf80,0x3ec40000,0x3ec43f35,0xbf6dbf35,0xbec4bf35,0x3f6d3f35,
0xbec40000,0xbf6dbf80,0x3ec40000,0x3f6d3f80,0xbf6dbf35,0xbec4bf35,0x3f6d3f35,0x3ec43f35,0x3ef10000,0x3f623f80,0xbf75bf35,0xbe95bf35,
0x3f7f3f55,0x3dc93f0e,0xbf46bf7b,0x3f223e48,0x3f223f6d,0xbf46bec4,0x3dc9bec4,0x3f7f3f6d,0xbe953e48,0xbf75bf7b,0x3f623f0e,0x3ef13f55,
0xbf55bf80,0x3f0e0000,0xbf0e0000,0xbf55bf80,0x3e48bec4,0x3f7b3f6d,0xbf7bbf6d,0x3e48bec4,0x3f7b3f35,0x3e483f35,0xbe48bf35,0x3f7b3f35,
0x3f0e3f6d,0xbf55bec4,0x3f553ec4,0x3f0e3f6d,0xbf220000,0xbf46bf80,0x3dc93f35,0xbf7fbf35,0xbf62bf7b,0x3ef1be48,0xbf75bf0e,0xbe95bf55,
0x3e95bec4,0x3f753f6d,0xbef1bf6d,0x3f623ec4,0x3f7f3f55,0xbdc93f0e,0x3f463e48,0x3f223f7b,0x3f353f80,0xbf350000,0x3f353f80,0xbf350000,
0xbf350000,0xbf35bf80,0xbf350000,0xbf35bf80,0xbf35bf80,0x3f350000,0xbf35bf80,0x3f350000,0x3f350000,0x3f353f80,0x3f350000,0x3f353f80,
0x3f460000,0x3f223f80,0x3f7f3f35,0xbdc93f35,0x3ef13f7b,0xbf62be48,0xbe953f0e,0xbf75bf55,0xbf75bec4,0xbe95bf6d,0xbf62bf6d,0x3ef1bec4,
0xbdc9bf55,0x3f7f3f0e,0x3f22be48,0x3f463f7b,0xbf0ebf80,0x3f550000,0x3f550000,0x3f0e3f80,0x3f7b3ec4,0x3e483f6d,0x3e483f6d,0xbf7bbec4,
0xbe483f35,0xbf7bbf35,0xbf7bbf35,0x3e48bf35,0xbf55bf6d,0x3f0ebec4,0x3f0ebec4,0x3f553f6d,0xbf620000,0xbef1bf80,0x3e95bf35,0x3f753f35,
0x3dc9bf55,0x3f7f3f0e,0x3f223f7b,0xbf463e48,0x3f463f6d,0xbf223ec4,0xbf7fbec4,0xbdc9bf6d,0xbf75be48,0xbe95bf7b,0x3ef1bf0e,0x3f623f55,
0x3ec43f80,0xbf6d0000,0xbec4bf80,0x3f6d0000,0xbf6dbf35,0x3ec4bf35,0x3f6d3f35,0xbec43f35,0x3f6d0000,0x3ec43f80,0xbf6d0000,0xbec4bf80,
0xbec43f35,0xbf6dbf35,0x3ec4bf35,0x3f6d3f35,0x3f750000,0x3e953f80,0xbf62bf35,0x3ef1bf35,0xbf223f0e,0xbf46bf55,0x3f7f3e48,0x3dc93f7b,
0x3dc9bf6d,0x3f7f3ec4,0xbf463ec4,0xbf22bf6d,0x3ef13f7b,0xbf623e48,0x3e95bf55,0x3f753f0e,0xbe48bf80,0x3f7b0000,0xbf7b0000,0xbe48bf80,
0x3f0e3f6d,0xbf553ec4,0x3f55bec4,0x3f0e3f6d,0xbf55bf35,0x3f0ebf35,0xbf0e3f35,0xbf55bf35,0x3f7b3ec4,0xbe483f6d,0x3e48bf6d,0x3f7b3ec4,
0xbf7f0000,0xbdc9bf80,0xbf223f35,0xbf46bf35,0x3f75be48,0x3e953f7b,0x3ef1bf55,0x3f623f0e,0xbf623ec4,0xbef1bf6d,0xbe953f6d,0xbf75bec4,
0x3f46bf0e,0x3f223f55,0x3dc9bf7b,0x3f7f3e48,0x3f80,0xbf800000,0x3f80,0xbf800000,0xbf80,0x3f800000,0xbf80,0x3f800000,
0x3f80,0xbf800000,0x3f80,0xbf800000,0xbf80,0x3f800000,0xbf80,0x3f800000,0x3f7f0000,0xbdc93f80,0x3f223f35,0xbf463f35,
0xbf75be48,0x3e95bf7b,0xbef1bf55,0x3f62bf0e,0x3f623ec4,0xbef13f6d,0x3e953f6d,0xbf753ec4,0xbf46bf0e,0x3f22bf55,0xbdc9bf7b,0x3f7fbe48,
0x3e48bf80,0x3f7b0000,0x3f7b0000,0xbe483f80,0xbf0e3f6d,0xbf55bec4,0xbf55bec4,0x3f0ebf6d,0x3f55bf35,0x3f0e3f35,0x3f0e3f35,0xbf553f35,
0xbf7b3ec4,0xbe48bf6d,0xbe48bf6d,0x3f7bbec4,0xbf750000,0x3e95bf80,0x3f62bf35,0x3ef13f35,0x3f223f0e,0xbf463f55,0xbf7f3e48,0x3dc9bf7b,
0xbdc9bf6d,0x3f7fbec4,0x3f463ec4,0xbf223f6d,0xbef13f7b,0xbf62be48,0xbe95bf55,0x3f75bf0e,0xbec43f80,0xbf6d0000,0x3ec4bf80,0x3f6d0000,
0x3f6dbf35,0x3ec43f35,0xbf6d3f35,0xbec4bf35,0xbf6d0000,0x3ec4bf80,0x3f6d0000,0xbec43f80,0x3ec43f35,0xbf6d3f35,0xbec4bf35,0x3f6dbf35,
0x3f620000,0xbef13f80,0xbe95bf35,0x3f75bf35,0xbdc9bf55,0x3f7fbf0e,0xbf223f7b,0xbf46be48,0xbf463f6d,0xbf22bec4,0x3f7fbec4,0xbdc93f6d,
0x3f75be48,0xbe953f7b,0xbef1bf0e,0x3f62bf55,0x3f0ebf80,0x3f550000,0xbf550000,0x3f0ebf80,0xbf7b3ec4,0x3e48bf6d,0xbe483f6d,0xbf7b3ec4,
0x3e483f35,0xbf7b3f35,0x3f7bbf35,0x3e483f35,0x3f55bf6d,0x3f0e3ec4,0xbf0ebec4,0x3f55bf6d,0xbf460000,0x3f22bf80,0xbf7f3f35,0xbdc9bf35,
0xbef13f7b,0xbf623e48,0x3e953f0e,0xbf753f55,0x3f75bec4,0xbe953f6d,0x3f62bf6d,0x3ef13ec4,0x3dc9bf55,0x3f7fbf0e,0xbf22be48,0x3f46bf7b,
0xbf353f80,0xbf350000,0xbf353f80,0xbf350000,0x3f350000,0xbf353f80,0x3f350000,0xbf353f80,0x3f35bf80,0x3f350000,0x3f35bf80,0x3f350000,
0xbf350000,0x3f35bf80,0xbf350000,0x3f35bf80,0x3f220000,0xbf463f80,0xbdc93f35,0xbf7f3f35,0x3f62bf7b,0x3ef13e48,0x3f75bf0e,0xbe953f55,
0xbe95bec4,0x3f75bf6d,0x3ef1bf6d,0x3f62bec4,0xbf7f3f55,0xbdc9bf0e,0xbf463e48,0x3f22bf7b,0x3f55bf80,0x3f0e0000,0x3f0e0000,0xbf553f80,
0xbe48bec4,0x3f7bbf6d,0x3f7bbf6d,0x3e483ec4,0xbf7b3f35,0x3e48bf35,0x3e48bf35,0x3f7bbf35,0xbf0e3f6d,0xbf553ec4,0xbf553ec4,0x3f0ebf6d,
0xbef10000,0x3f62bf80,0x3f75bf35,0xbe953f35,0xbf7f3f55,0x3dc9bf0e,0x3f46bf7b,0x3f22be48,0xbf223f6d,0xbf463ec4,0xbdc9bec4,0x3f7fbf6d,
0x3e953e48,0xbf753f7b,0xbf623f0e,0x3ef1bf55,0xbf6d3f80,0xbec40000,0x3f6dbf80,0x3ec40000,0xbec43f35,0xbf6d3f35,0x3ec4bf35,0x3f6dbf35,
0x3ec40000,0xbf6d3f80,0xbec40000,0x3f6dbf80,0x3f6dbf35,0xbec43f35,0xbf6d3f35,0x3ec4bf35,0x3e950000,0xbf753f80,0x3ef1bf35,0x3f62bf35,
0x3f46bf0e,0xbf223f55,0xbdc9be48,0x3f7fbf7b,0x3f7fbf6d,0xbdc93ec4,0xbf223ec4,0x3f46bf6d,0x3f62bf7b,0x3ef1be48,0xbf753f55,0x3e95bf0e,
0x3f7bbf80,0x3e480000,0xbe480000,0x3f7bbf80,0x3f55bf6d,0x3f0ebec4,0xbf0e3ec4,0x3f55bf6d,0x3f0ebf35,0x3f55bf35,0xbf553f35,0x3f0ebf35,
0x3e48bec4,0x3f7bbf6d,0xbf7b3f6d,0x3e48bec4,0xbdc90000,0x3f7fbf80,0xbf463f35,0x3f22bf35,0xbe953e48,0x3f75bf7b,0xbf623f55,0x3ef1bf0e,
0xbef13ec4,0x3f62bf6d,0xbf753f6d,0x3e95bec4,0xbf223f0e,0x3f46bf55,0xbf7f3f7b,0x3dc9be48,0x40003f80,0x3fb53f80,0x3f80,0xbfb53f80,
0x40004000,0xbfb50000,0x0,0xbfb5c000,0x40004000,0xbfb5c000,0x0,0x3fb50000,0x40004000,0x3fb50000,0x0,0x3fb54000,
0x3fff3f80,0x3fa23f80,0xbe49bf80,0xbfc6bf80,0x3ff53ffb,0xbfe2bec8,0xbf15bec8,0xbf71bffb,0x3fe23fed,0xbf15bfed,0xbf71bf44,0x3ff53f44,
0x3fc63fd5,0x3fff3f8e,0xbfa2bf8e,0x3e493fd5,0x3ffb3f80,0x3f8e3f80,0xbec83f80,0xbfd53f80,0x3fd53fed,0xbffbbf44,0xbf8ebf44,0xbec8bfed,
0x3f8e3fb5,0x3ec8bfb5,0xbfd5bfb5,0x3ffb3fb5,0x3ec83f44,0x3fd53fed,0xbffbbfed,0xbf8e3f44,0x3ff53f80,0x3f713f80,0xbf15bf80,0xbfe2bf80,
0x3fa23fd5,0xbfffbf8e,0xbfc6bf8e,0x3e49bfd5,0x3e493f44,0x3fa2bf44,0xbfffbfed,0x3fc63fed,0xbf71bec8,0x3f153ffb,0xbfe2bffb,0xbff5bec8,
0x3fed3f80,0x3f443f80,0xbf443f80,0xbfed3f80,0x3f443fb5,0xbfedbfb5,0xbfedbfb5,0x3f44bfb5,0xbf440000,0x3fed0000,0xbfedc000,0x3f444000,
0xbfedbfb5,0xbf443fb5,0xbf44bfb5,0xbfedbfb5,0x3fe23f80,0x3f153f80,0xbf71bf80,0xbff5bf80,0x3e493f8e,0xbfc6bfd5,0xbfffbfd5,0x3fa2bf8e,
0xbfc6bf44,0x3fff3f44,0xbfa2bfed,0xbe493fed,0xbff5bffb,0xbfe23ec8,0x3f15bec8,0xbf71bffb,0x3fd53f80,0x3ec83f80,0xbf8e3f80,0xbffb3f80,
0xbec83f44,0xbf8ebfed,0xbffbbfed,0x3fd5bf44,0xbffbbfb5,0x3fd53fb5,0xbec8bfb5,0xbf8e3fb5,0xbf8ebfed,0xbffbbf44,0x3fd53f44,0x3ec8bfed,
0x3fc63f80,0x3e493f80,0xbfa2bf80,0xbfffbf80,0xbf713ec8,0xbf15bffb,0xbfe2bffb,0x3ff5bec8,0xbff5bfed,0x3f713fed,0x3f15bf44,0xbfe23f44,
0x3e49bf8e,0xbfa2bfd5,0x3fff3fd5,0x3fc6bf8e,0x3f80,0xbfb53f80,0xc0003f80,0xbfb53f80,0xc000,0x3fb50000,0x40000000,0xbfb54000,
0x4000,0x3fb5c000,0xc0000000,0x3fb50000,0xc000,0xbfb50000,0x40000000,0x3fb5c000,0xbe493f80,0xbfc63f80,0xbfffbf80,0xbfa2bf80,
0x3f15bffb,0x3f713ec8,0x3ff53ec8,0xbfe23ffb,0xbf713fed,0x3ff5bfed,0xbfe2bf44,0x3f153f44,0x3fa2bfd5,0xbe49bf8e,0x3fc63f8e,0x3fffbfd5,
0xbec83f80,0xbfd53f80,0xbffb3f80,0xbf8e3f80,0x3f8ebfed,0x3ec83f44,0x3fd53f44,0xbffb3fed,0xbfd53fb5,0x3ffbbfb5,0xbf8ebfb5,0xbec83fb5,
0x3ffbbf44,0x3f8ebfed,0x3ec83fed,0x3fd5bf44,0xbf153f80,0xbfe23f80,0xbff5bf80,0xbf71bf80,0x3fc6bfd5,0xbe493f8e,0x3fa23f8e,0xbfff3fd5,
0xbfff3f44,0x3fc6bf44,0xbe49bfed,0xbfa23fed,0x3fe23ec8,0x3ff5bffb,0xbf713ffb,0x3f153ec8,0xbf443f80,0xbfed3f80,0xbfed3f80,0xbf443f80,
0x3fedbfb5,0xbf443fb5,0x3f443fb5,0xbfed3fb5,0xbfed0000,0x3f440000,0x3f44c000,0xbfed4000,0x3f443fb5,0x3fedbfb5,0xbfed3fb5,0xbf443fb5,
0xbf713f80,0xbff53f80,0xbfe2bf80,0xbf15bf80,0x3fffbf8e,0xbfa23fd5,0x3e493fd5,0xbfc63f8e,0xbfa2bf44,0xbe493f44,0x3fc6bfed,0xbfff3fed,
0xbf153ffb,0x3f71bec8,0xbff53ec8,0xbfe23ffb,0xbf8e3f80,0xbffb3f80,0xbfd53f80,0xbec83f80,0x3ffbbf44,0xbfd53fed,0xbec83fed,0xbf8e3f44,
0xbec8bfb5,0xbf8e3fb5,0x3ffbbfb5,0xbfd53fb5,0xbfd53fed,0xbec83f44,0xbf8ebf44,0xbffb3fed,0xbfa23f80,0xbfff3f80,0xbfc6bf80,0xbe49bf80,
0x3fe2bec8,0xbff53ffb,0xbf713ffb,0xbf153ec8,0x3f15bfed,0xbfe23fed,0x3ff5bf44,0xbf713f44,0xbfff3f8e,0xbfc63fd5,0x3e49bfd5,0xbfa23f8e,
0xc0003f80,0xbfb53f80,0x3f80,0x3fb53f80,0xc0004000,0x3fb50000,0x0,0x3fb5c000,0xc0004000,0x3fb5c000,0x0,0xbfb50000,
0xc0004000,0xbfb50000,0x0,0xbfb54000,0xbfff3f80,0xbfa23f80,0x3e49bf80,0x3fc6bf80,0xbff53ffb,0x3fe2bec8,0x3f15bec8,0x3f71bffb,
0xbfe23fed,0x3f15bfed,0x3f71bf44,0xbff53f44,0xbfc63fd5,0xbfff3f8e,0x3fa2bf8e,0xbe493fd5,0xbffb3f80,0xbf8e3f80,0x3ec83f80,0x3fd53f80,
0xbfd53fed,0x3ffbbf44,0x3f8ebf44,0x3ec8bfed,0xbf8e3fb5,0xbec8bfb5,0x3fd5bfb5,0xbffb3fb5,0xbec83f44,0xbfd53fed,0x3ffbbfed,0x3f8e3f44,
0xbff53f80,0xbf713f80,0x3f15bf80,0x3fe2bf80,0xbfa23fd5,0x3fffbf8e,0x3fc6bf8e,0xbe49bfd5,0xbe493f44,0xbfa2bf44,0x3fffbfed,0xbfc63fed,
0x3f71bec8,0xbf153ffb,0x3fe2bffb,0x3ff5bec8,0xbfed3f80,0xbf443f80,0x3f443f80,0x3fed3f80,0xbf443fb5,0x3fedbfb5,0x3fedbfb5,0xbf44bfb5,
0x3f440000,0xbfed0000,0x3fedc000,0xbf444000,0x3fedbfb5,0x3f443fb5,0x3f44bfb5,0x3fedbfb5,0xbfe23f80,0xbf153f80,0x3f71bf80,0x3ff5bf80,
0xbe493f8e,0x3fc6bfd5,0x3fffbfd5,0xbfa2bf8e,0x3fc6bf44,0xbfff3f44,0x3fa2bfed,0x3e493fed,0x3ff5bffb,0x3fe23ec8,0xbf15bec8,0x3f71bffb,
0xbfd53f80,0xbec83f80,0x3f8e3f80,0x3ffb3f80,0x3ec83f44,0x3f8ebfed,0x3ffbbfed,0xbfd5bf44,0x3ffbbfb5,0xbfd53fb5,0x3ec8bfb5,0x3f8e3fb5,
0x3f8ebfed,0x3ffbbf44,0xbfd53f44,0xbec8bfed,0xbfc63f80,0xbe493f80,0x3fa2bf80,0x3fffbf80,0x3f713ec8,0x3f15bffb,0x3fe2bffb,0xbff5bec8,
0x3ff5bfed,0xbf713fed,0xbf15bf44,0x3fe23f44,0xbe49bf8e,0x3fa2bfd5,0xbfff3fd5,0xbfc6bf8e,0x3f80,0x3fb53f80,0x40003f80,0x3fb53f80,
0xc000,0xbfb50000,0xc0000000,0x3fb54000,0x4000,0xbfb5c000,0x40000000,0xbfb50000,0xc000,0x3fb50000,0xc0000000,0xbfb5c000,
0x3e493f80,0x3fc63f80,0x3fffbf80,0x3fa2bf80,0xbf15bffb,0xbf713ec8,0xbff53ec8,0x3fe23ffb,0x3f713fed,0xbff5bfed,0x3fe2bf44,0xbf153f44,
0xbfa2bfd5,0x3e49bf8e,0xbfc63f8e,0xbfffbfd5,0x3ec83f80,0x3fd53f80,0x3ffb3f80,0x3f8e3f80,0xbf8ebfed,0xbec83f44,0xbfd53f44,0x3ffb3fed,
0x3fd53fb5,0xbffbbfb5,0x3f8ebfb5,0x3ec83fb5,0xbffbbf44,0xbf8ebfed,0xbec83fed,0xbfd5bf44,0x3f153f80,0x3fe23f80,0x3ff5bf80,0x3f71bf80,
0xbfc6bfd5,0x3e493f8e,0xbfa23f8e,0x3fff3fd5,0x3fff3f44,0xbfc6bf44,0x3e49bfed,0x3fa23fed,0xbfe23ec8,0xbff5bffb,0x3f713ffb,0xbf153ec8,
0x3f443f80,0x3fed3f80,0x3fed3f80,0x3f443f80,0xbfedbfb5,0x3f443fb5,0xbf443fb5,0x3fed3fb5,0x3fed0000,0xbf440000,0xbf44c000,0x3fed4000,
0xbf443fb5,0xbfedbfb5,0x3fed3fb5,0x3f443fb5,0x3f713f80,0x3ff53f80,0x3fe2bf80,0x3f15bf80,0xbfffbf8e,0x3fa23fd5,0xbe493fd5,0x3fc63f8e,
0x3fa2bf44,0x3e493f44,0xbfc6bfed,0x3fff3fed,0x3f153ffb,0xbf71bec8,0x3ff53ec8,0x3fe23ffb,0x3f8e3f80,0x3ffb3f80,0x3fd53f80,0x3ec83f80,
0xbffbbf44,0x3fd53fed,0x3ec83fed,0x3f8e3f44,0x3ec8bfb5,0x3f8e3fb5,0xbffbbfb5,0x3fd53fb5,0x3fd53fed,0x3ec83f44,0x3f8ebf44,0x3ffb3fed,
0x3fa23f80,0x3fff3f80,0x3fc6bf80,0x3e49bf80,0xbfe2bec8,0x3ff53ffb,0x3f713ffb,0x3f153ec8,0xbf15bfed,0x3fe23fed,0xbff5bf44,0x3f713f44,
0x3fff3f8e,0x3fc63fd5,0xbe49bfd5,0x3fa23f8e,0x40004000,0x3fb54000,0x0,0xbfb50000,0x40004000,0xbfb50000,0x0,0xbfb5c000,
0x40004000,0xbfb5c000,0x0,0x3fb50000,0x40004000,0x3fb50000,0x0,0x3fb54000,0x3fa23fb5,0xbe493fb5,0xbfc6bfb5,0xbfffbfb5,
0x3f713f8e,0xbff5bfd5,0xbfe2bfd5,0x3f15bf8e,0x3f153f44,0x3f71bf44,0xbff5bfed,0x3fe23fed,0x3e493ec8,0x3fc63ffb,0xbfffbffb,0xbfa23ec8,
0xbec80000,0xbfd50000,0xbffbc000,0xbf8ec000,0xbf8ebf44,0xbec8bfed,0xbfd5bfed,0x3ffb3f44,0xbfd5bfb5,0x3ffb3fb5,0xbf8ebfb5,0xbec83fb5,
0xbffbbfed,0xbf8e3f44,0xbec8bf44,0xbfd5bfed,0xbfe2bfb5,0xbff5bfb5,0xbf71bfb5,0x3f15bfb5,0xbfffbffb,0x3fc6bec8,0x3e49bec8,0x3fa23ffb,
0xbfc6bfed,0x3e493fed,0x3fa23f44,0xbfffbf44,0xbf15bf8e,0xbfe2bfd5,0x3ff53fd5,0x3f71bf8e,0xbfedc000,0xbf44c000,0x3f440000,0x3fed0000,
0xbf44bfb5,0x3fed3fb5,0x3fed3fb5,0xbf443fb5,0x3f440000,0xbfed0000,0x3fed4000,0xbf44c000,0x3fed3fb5,0x3f44bfb5,0x3f443fb5,0x3fed3fb5,
0xbf15bfb5,0x3f71bfb5,0x3ff53fb5,0x3fe23fb5,0x3fa23ec8,0x3e493ffb,0x3fc63ffb,0xbfffbec8,0x3fff3fed,0xbfa2bfed,0xbe493f44,0x3fc6bf44,
0x3f713fd5,0x3ff53f8e,0xbfe2bf8e,0xbf153fd5,0x3f8e0000,0x3ffb0000,0x3fd54000,0x3ec84000,0x3ffb3fed,0xbfd53f44,0xbec83f44,0xbf8ebfed,
0x3ec83fb5,0x3f8ebfb5,0xbffbbfb5,0x3fd53fb5,0xbfd5bf44,0xbec83fed,0xbf8ebfed,0xbffbbf44,0x3fff3fb5,0x3fc63fb5,0x3e493fb5,0xbfa23fb5,
0x3f153fd5,0xbfe2bf8e,0xbff5bf8e,0x3f71bfd5,0xbfe2bf44,0x3ff53f44,0xbf71bfed,0xbf153fed,0xbfa2bffb,0xbfffbec8,0x3fc63ec8,0x3e49bffb,
0x4000,0xbfb54000,0xc0000000,0xbfb50000,0xc000,0x3fb50000,0x40000000,0xbfb54000,0x4000,0x3fb5c000,0xc0000000,0x3fb50000,
0xc000,0xbfb50000,0x40000000,0x3fb5c000,0xbfc63fb5,0xbfff3fb5,0xbfa2bfb5,0x3e49bfb5,0x3fe2bf8e,0xbf153fd5,0x3f713fd5,0xbff53f8e,
0xbff53f44,0x3fe2bf44,0xbf15bfed,0xbf713fed,0x3fffbec8,0x3fa2bffb,0x3e493ffb,0x3fc6bec8,0xbffb0000,0xbf8e0000,0x3ec8c000,0x3fd5c000,
0x3fd53f44,0xbffb3fed,0xbf8e3fed,0xbec8bf44,0xbf8ebfb5,0xbec83fb5,0x3fd5bfb5,0xbffb3fb5,0x3ec83fed,0x3fd5bf44,0xbffb3f44,0xbf8e3fed,
0xbf71bfb5,0x3f15bfb5,0x3fe2bfb5,0x3ff5bfb5,0xbe493ffb,0xbfa23ec8,0xbfff3ec8,0x3fc6bffb,0x3fa2bfed,0xbfff3fed,0x3fc63f44,0xbe49bf44,
0xbff53f8e,0xbf713fd5,0xbf15bfd5,0xbfe23f8e,0x3f44c000,0x3fedc000,0x3fed0000,0x3f440000,0xbfed3fb5,0x3f44bfb5,0xbf44bfb5,0x3fedbfb5,
0x3fed0000,0xbf440000,0xbf444000,0x3fedc000,0xbf44bfb5,0xbfed3fb5,0x3fedbfb5,0x3f44bfb5,0x3ff5bfb5,0x3fe2bfb5,0x3f153fb5,0xbf713fb5,
0xbfc6bec8,0x3fffbffb,0x3fa2bffb,0x3e493ec8,0xbe493fed,0x3fc6bfed,0xbfff3f44,0x3fa2bf44,0x3fe2bfd5,0x3f15bf8e,0x3f713f8e,0x3ff5bfd5,
0x3fd50000,0x3ec80000,0xbf8e4000,0xbffb4000,0x3ec8bfed,0x3f8ebf44,0x3ffbbf44,0xbfd53fed,0xbffb3fb5,0x3fd5bfb5,0xbec8bfb5,0xbf8e3fb5,
0x3f8e3f44,0x3ffbbfed,0xbfd53fed,0xbec83f44,0x3e493fb5,0xbfa23fb5,0xbfff3fb5,0xbfc63fb5,0x3ff5bfd5,0xbf713f8e,0x3f153f8e,0xbfe23fd5,
0xbf71bf44,0xbf153f44,0x3fe2bfed,0xbff53fed,0xbfc63ffb,0xbe493ec8,0xbfa2bec8,0xbfff3ffb,0xc0004000,0xbfb54000,0x0,0x3fb50000,
0xc0004000,0x3fb50000,0x0,0x3fb5c000,0xc0004000,0x3fb5c000,0x0,0xbfb50000,0xc0004000,0xbfb50000,0x0,0xbfb54000,
0xbfa23fb5,0x3e493fb5,0x3fc6bfb5,0x3fffbfb5,0xbf713f8e,0x3ff5bfd5,0x3fe2bfd5,0xbf15bf8e,0xbf153f44,0xbf71bf44,0x3ff5bfed,0xbfe23fed,
0xbe493ec8,0xbfc63ffb,0x3fffbffb,0x3fa23ec8,0x3ec80000,0x3fd50000,0x3ffbc000,0x3f8ec000,0x3f8ebf44,0x3ec8bfed,0x3fd5bfed,0xbffb3f44,
0x3fd5bfb5,0xbffb3fb5,0x3f8ebfb5,0x3ec83fb5,0x3ffbbfed,0x3f8e3f44,0x3ec8bf44,0x3fd5bfed,0x3fe2bfb5,0x3ff5bfb5,0x3f71bfb5,0xbf15bfb5,
0x3fffbffb,0xbfc6bec8,0xbe49bec8,0xbfa23ffb,0x3fc6bfed,0xbe493fed,0xbfa23f44,0x3fffbf44,0x3f15bf8e,0x3fe2bfd5,0xbff53fd5,0xbf71bf8e,
0x3fedc000,0x3f44c000,0xbf440000,0xbfed0000,0x3f44bfb5,0xbfed3fb5,0xbfed3fb5,0x3f443fb5,0xbf440000,0x3fed0000,0xbfed4000,0x3f44c000,
0xbfed3fb5,0xbf44bfb5,0xbf443fb5,0xbfed3fb5,0x3f15bfb5,0xbf71bfb5,0xbff53fb5,0xbfe23fb5,0xbfa23ec8,0xbe493ffb,0xbfc63ffb,0x3fffbec8,
0xbfff3fed,0x3fa2bfed,0x3e493f44,0xbfc6bf44,0xbf713fd5,0xbff53f8e,0x3fe2bf8e,0x3f153fd5,0xbf8e0000,0xbffb0000,0xbfd54000,0xbec84000,
0xbffb3fed,0x3fd53f44,0x3ec83f44,0x3f8ebfed,0xbec83fb5,0xbf8ebfb5,0x3ffbbfb5,0xbfd53fb5,0x3fd5bf44,0x3ec83fed,0x3f8ebfed,0x3ffbbf44,
0xbfff3fb5,0xbfc63fb5,0xbe493fb5,0x3fa23fb5,0xbf153fd5,0x3fe2bf8e,0x3ff5bf8e,0xbf71bfd5,0x3fe2bf44,0xbff53f44,0x3f71bfed,0x3f153fed,
0x3fa2bffb,0x3fffbec8,0xbfc63ec8,0xbe49bffb,0x4000,0x3fb54000,0x40000000,0x3fb50000,0xc000,0xbfb50000,0xc0000000,0x3fb54000,
0x4000,0xbfb5c000,0x40000000,0xbfb50000,0xc000,0x3fb50000,0xc0000000,0xbfb5c000,0x3fc63fb5,0x3fff3fb5,0x3fa2bfb5,0xbe49bfb5,
0xbfe2bf8e,0x3f153fd5,0xbf713fd5,0x3ff53f8e,0x3ff53f44,0xbfe2bf44,0x3f15bfed,0x3f713fed,0xbfffbec8,0xbfa2bffb,0xbe493ffb,0xbfc6bec8,
0x3ffb0000,0x3f8e0000,0xbec8c000,0xbfd5c000,0xbfd53f44,0x3ffb3fed,0x3f8e3fed,0x3ec8bf44,0x3f8ebfb5,0x3ec83fb5,0xbfd5bfb5,0x3ffb3fb5,
0xbec83fed,0xbfd5bf44,0x3ffb3f44,0x3f8e3fed,0x3f71bfb5,0xbf15bfb5,0xbfe2bfb5,0xbff5bfb5,0x3e493ffb,0x3fa23ec8,0x3fff3ec8,0xbfc6bffb,
0xbfa2bfed,0x3fff3fed,0xbfc63f44,0x3e49bf44,0x3ff53f8e,0x3f713fd5,0x3f15bfd5,0x3fe23f8e,0xbf44c000,0xbfedc000,0xbfed0000,0xbf440000,
0x3fed3fb5,0xbf44bfb5,0x3f44bfb5,0xbfedbfb5,0xbfed0000,0x3f440000,0x3f444000,0xbfedc000,0x3f44bfb5,0x3fed3fb5,0xbfedbfb5,0xbf44bfb5,
0xbff5bfb5,0xbfe2bfb5,0xbf153fb5,0x3f713fb5,0x3fc6bec8,0xbfffbffb,0xbfa2bffb,0xbe493ec8,0x3e493fed,0xbfc6bfed,0x3fff3f44,0xbfa2bf44,
0xbfe2bfd5,0xbf15bf8e,0xbf713f8e,0xbff5bfd5,0xbfd50000,0xbec80000,0x3f8e4000,0x3ffb4000,0xbec8bfed,0xbf8ebf44,0xbffbbf44,0x3fd53fed,
0x3ffb3fb5,0xbfd5bfb5,0x3ec8bfb5,0x3f8e3fb5,0xbf8e3f44,0xbffbbfed,0x3fd53fed,0x3ec83f44,0xbe493fb5,0x3fa23fb5,0x3fff3fb5,0x3fc63fb5,
0xbff5bfd5,0x3f713f8e,0xbf153f8e,0x3fe23fd5,0x3f71bf44,0x3f153f44,0xbfe2bfed,0x3ff53fed,0x3fc63ffb,0x3e493ec8,0x3fa2bec8,0x3fff3ffb,
0x40004000,0x3fb54000,0x0,0xbfb50000,0x40004000,0xbfb50000,0x0,0xbfb5c000,0x40004000,0xbfb5c000,0x0,0x3fb50000,
0x40004000,0x3fb50000,0x0,0x3fb54000,0xbe490000,0xbfc60000,0xbfffc000,0xbfa2c000,0xbf15bec8,0xbf71bffb,0xbff5bffb,0x3fe23ec8,
0xbf71bf44,0x3ff53f44,0xbfe2bfed,0x3f153fed,0xbfa2bf8e,0x3e493fd5,0xbfc6bfd5,0xbfffbf8e,0xbffbc000,0xbf8ec000,0x3ec80000,0x3fd50000,
0xbfd5bfed,0x3ffb3f44,0x3f8e3f44,0x3ec83fed,0xbf8ebfb5,0xbec83fb5,0x3fd53fb5,0xbffbbfb5,0xbec8bf44,0xbfd5bfed,0x3ffb3fed,0x3f8ebf44,
0x3f150000,0x3fe20000,0x3ff54000,0x3f714000,0x3fc63f8e,0xbe493fd5,0x3fa23fd5,0xbfffbf8e,0x3fff3fed,0xbfc6bfed,0x3e493f44,0x3fa2bf44,
0x3fe23ffb,0x3ff53ec8,0xbf71bec8,0x3f153ffb,0x3fed4000,0x3f444000,0xbf440000,0xbfed0000,0x3f443fb5,0xbfedbfb5,0xbfedbfb5,0x3f44bfb5,
0xbf440000,0x3fed0000,0xbfedc000,0x3f444000,0xbfedbfb5,0xbf443fb5,0xbf44bfb5,0xbfedbfb5,0xbf710000,0xbff50000,0xbfe2c000,0xbf15c000,
0xbfffbfd5,0x3fa2bf8e,0xbe49bf8e,0x3fc63fd5,0xbfa2bfed,0xbe493fed,0x3fc63f44,0xbfffbf44,0x3f15bec8,0xbf71bffb,0x3ff53ffb,0x3fe2bec8,
0xbfd5c000,0xbec8c000,0x3f8e0000,0x3ffb0000,0x3ec8bf44,0x3f8e3fed,0x3ffb3fed,0xbfd53f44,0x3ffb3fb5,0xbfd5bfb5,0x3ec83fb5,0x3f8ebfb5,
0x3f8e3fed,0x3ffb3f44,0xbfd5bf44,0xbec83fed,0x3fa20000,0x3fff0000,0x3fc64000,0x3e494000,0x3fe23ffb,0xbff53ec8,0xbf713ec8,0xbf15bffb,
0xbf153f44,0x3fe2bf44,0xbff5bfed,0x3f713fed,0xbfffbfd5,0xbfc63f8e,0x3e49bf8e,0xbfa2bfd5,0x4000,0xbfb54000,0xc0000000,0xbfb50000,
0xc000,0x3fb50000,0x40000000,0xbfb54000,0x4000,0x3fb5c000,0xc0000000,0x3fb50000,0xc000,0xbfb50000,0x40000000,0x3fb5c000,
0xbfff0000,0xbfa20000,0x3e49c000,0x3fc6c000,0x3ff53ec8,0xbfe23ffb,0xbf153ffb,0xbf71bec8,0xbfe2bf44,0x3f153f44,0x3f71bfed,0xbff53fed,
0x3fc63f8e,0x3fffbfd5,0xbfa23fd5,0x3e493f8e,0x3ec8c000,0x3fd5c000,0x3ffb0000,0x3f8e0000,0xbf8e3fed,0xbec8bf44,0xbfd5bf44,0x3ffbbfed,
0x3fd5bfb5,0xbffb3fb5,0x3f8e3fb5,0x3ec8bfb5,0xbffb3f44,0xbf8e3fed,0xbec8bfed,0xbfd53f44,0x3ff50000,0x3f710000,0xbf154000,0xbfe24000,
0xbfa2bf8e,0x3fffbfd5,0x3fc6bfd5,0xbe493f8e,0x3e493fed,0x3fa2bfed,0xbfff3f44,0x3fc6bf44,0x3f71bffb,0xbf15bec8,0x3fe23ec8,0x3ff5bffb,
0xbf444000,0xbfed4000,0xbfed0000,0xbf440000,0x3fedbfb5,0xbf443fb5,0x3f443fb5,0xbfed3fb5,0xbfed0000,0x3f440000,0x3f44c000,0xbfed4000,
0x3f443fb5,0x3fedbfb5,0xbfed3fb5,0xbf443fb5,0xbfe20000,0xbf150000,0x3f71c000,0x3ff5c000,0x3e493fd5,0xbfc63f8e,0xbfff3f8e,0x3fa2bfd5,
0x3fc6bfed,0xbfff3fed,0x3fa23f44,0x3e49bf44,0xbff53ec8,0xbfe23ffb,0x3f15bffb,0xbf713ec8,0x3f8ec000,0x3ffbc000,0x3fd50000,0x3ec80000,
0xbffb3f44,0x3fd5bfed,0x3ec8bfed,0x3f8ebf44,0x3ec83fb5,0x3f8ebfb5,0xbffb3fb5,0x3fd5bfb5,0x3fd5bfed,0x3ec8bf44,0x3f8e3f44,0x3ffbbfed,
0x3fc60000,0x3e490000,0xbfa24000,0xbfff4000,0x3f71bffb,0x3f15bec8,0x3fe2bec8,0xbff53ffb,0xbff53f44,0x3f71bf44,0x3f15bfed,0xbfe23fed,
0xbe493fd5,0x3fa2bf8e,0xbfff3f8e,0xbfc63fd5,0xc0004000,0xbfb54000,0x0,0x3fb50000,0xc0004000,0x3fb50000,0x0,0x3fb5c000,
0xc0004000,0x3fb5c000,0x0,0xbfb50000,0xc0004000,0xbfb50000,0x0,0xbfb54000,0x3e490000,0x3fc60000,0x3fffc000,0x3fa2c000,
0x3f15bec8,0x3f71bffb,0x3ff5bffb,0xbfe23ec8,0x3f71bf44,0xbff53f44,0x3fe2bfed,0xbf153fed,0x3fa2bf8e,0xbe493fd5,0x3fc6bfd5,0x3fffbf8e,
0x3ffbc000,0x3f8ec000,0xbec80000,0xbfd50000,0x3fd5bfed,0xbffb3f44,0xbf8e3f44,0xbec83fed,0x3f8ebfb5,0x3ec83fb5,0xbfd53fb5,0x3ffbbfb5,
0x3ec8bf44,0x3fd5bfed,0xbffb3fed,0xbf8ebf44,0xbf150000,0xbfe20000,0xbff54000,0xbf714000,0xbfc63f8e,0x3e493fd5,0xbfa23fd5,0x3fffbf8e,
0xbfff3fed,0x3fc6bfed,0xbe493f44,0xbfa2bf44,0xbfe23ffb,0xbff53ec8,0x3f71bec8,0xbf153ffb,0xbfed4000,0xbf444000,0x3f440000,0x3fed0000,
0xbf443fb5,0x3fedbfb5,0x3fedbfb5,0xbf44bfb5,0x3f440000,0xbfed0000,0x3fedc000,0xbf444000,0x3fedbfb5,0x3f443fb5,0x3f44bfb5,0x3fedbfb5,
0x3f710000,0x3ff50000,0x3fe2c000,0x3f15c000,0x3fffbfd5,0xbfa2bf8e,0x3e49bf8e,0xbfc63fd5,0x3fa2bfed,0x3e493fed,0xbfc63f44,0x3fffbf44,
0xbf15bec8,0x3f71bffb,0xbff53ffb,0xbfe2bec8,0x3fd5c000,0x3ec8c000,0xbf8e0000,0xbffb0000,0xbec8bf44,0xbf8e3fed,0xbffb3fed,0x3fd53f44,
0xbffb3fb5,0x3fd5bfb5,0xbec83fb5,0xbf8ebfb5,0xbf8e3fed,0xbffb3f44,0x3fd5bf44,0x3ec83fed,0xbfa20000,0xbfff0000,0xbfc64000,0xbe494000,
0xbfe23ffb,0x3ff53ec8,0x3f713ec8,0x3f15bffb,0x3f153f44,0xbfe2bf44,0x3ff5bfed,0xbf713fed,0x3fffbfd5,0x3fc63f8e,0xbe49bf8e,0x3fa2bfd5,
0x4000,0x3fb54000,0x40000000,0x3fb50000,0xc000,0xbfb50000,0xc0000000,0x3fb54000,0x4000,0xbfb5c000,0x40000000,0xbfb50000,
0xc000,0x3fb50000,0xc0000000,0xbfb5c000,0x3fff0000,0x3fa20000,0xbe49c000,0xbfc6c000,0xbff53ec8,0x3fe23ffb,0x3f153ffb,0x3f71bec8,
0x3fe2bf44,0xbf153f44,0xbf71bfed,0x3ff53fed,0xbfc63f8e,0xbfffbfd5,0x3fa23fd5,0xbe493f8e,0xbec8c000,0xbfd5c000,0xbffb0000,0xbf8e0000,
0x3f8e3fed,0x3ec8bf44,0x3fd5bf44,0xbffbbfed,0xbfd5bfb5,0x3ffb3fb5,0xbf8e3fb5,0xbec8bfb5,0x3ffb3f44,0x3f8e3fed,0x3ec8bfed,0x3fd53f44,
0xbff50000,0xbf710000,0x3f154000,0x3fe24000,0x3fa2bf8e,0xbfffbfd5,0xbfc6bfd5,0x3e493f8e,0xbe493fed,0xbfa2bfed,0x3fff3f44,0xbfc6bf44,
0xbf71bffb,0x3f15bec8,0xbfe23ec8,0xbff5bffb,0x3f444000,0x3fed4000,0x3fed0000,0x3f440000,0xbfedbfb5,0x3f443fb5,0xbf443fb5,0x3fed3fb5,
0x3fed0000,0xbf440000,0xbf44c000,0x3fed4000,0xbf443fb5,0xbfedbfb5,0x3fed3fb5,0x3f443fb5,0x3fe20000,0x3f150000,0xbf71c000,0xbff5c000,
0xbe493fd5,0x3fc63f8e,0x3fff3f8e,0xbfa2bfd5,0xbfc6bfed,0x3fff3fed,0xbfa23f44,0xbe49bf44,0x3ff53ec8,0x3fe23ffb,0xbf15bffb,0x3f713ec8,
0xbf8ec000,0xbffbc000,0xbfd50000,0xbec80000,0x3ffb3f44,0xbfd5bfed,0xbec8bfed,0xbf8ebf44,0xbec83fb5,0xbf8ebfb5,0x3ffb3fb5,0xbfd5bfb5,
0xbfd5bfed,0xbec8bf44,0xbf8e3f44,0xbffbbfed,0xbfc60000,0xbe490000,0x3fa24000,0x3fff4000,0xbf71bffb,0xbf15bec8,0xbfe2bec8,0x3ff53ffb,
0x3ff53f44,0xbf71bf44,0xbf15bfed,0x3fe23fed,0x3e493fd5,0xbfa2bf8e,0x3fff3f8e,0x3fc63fd5,0x40004000,0x3fb54000,0x0,0xbfb50000,
0x40004000,0xbfb50000,0x0,0xbfb5c000,0x40004000,0xbfb5c000,0x0,0x3fb50000,0x40004000,0x3fb50000,0x0,0x3fb54000,
0xbfc6bfb5,0xbfffbfb5,0xbfa2bfb5,0x3e49bfb5,0xbfe2bfd5,0x3f15bf8e,0xbf71bf8e,0x3ff53fd5,0xbff5bfed,0x3fe23fed,0xbf15bf44,0xbf713f44,
0xbfffbffb,0xbfa23ec8,0xbe49bec8,0xbfc6bffb,0x3ec80000,0x3fd50000,0x3ffb4000,0x3f8e4000,0x3f8e3f44,0x3ec83fed,0x3fd53fed,0xbffbbf44,
0x3fd53fb5,0xbffbbfb5,0x3f8e3fb5,0x3ec8bfb5,0x3ffb3fed,0x3f8ebf44,0x3ec83f44,0x3fd53fed,0x3f713fb5,0xbf153fb5,0xbfe2bfb5,0xbff5bfb5,
0xbe493ec8,0xbfa2bffb,0xbfffbffb,0x3fc6bec8,0xbfa2bf44,0x3fff3f44,0xbfc6bfed,0x3e493fed,0xbff5bfd5,0xbf713f8e,0xbf15bf8e,0xbfe2bfd5,
0xbfedc000,0xbf44c000,0x3f440000,0x3fed0000,0xbf44bfb5,0x3fed3fb5,0x3fed3fb5,0xbf443fb5,0x3f440000,0xbfed0000,0x3fed4000,0xbf44c000,
0x3fed3fb5,0x3f44bfb5,0x3f443fb5,0x3fed3fb5,0x3ff53fb5,0x3fe23fb5,0x3f153fb5,0xbf713fb5,0x3fc63ffb,0xbfffbec8,0xbfa2bec8,0xbe49bffb,
0xbe493f44,0x3fc6bf44,0xbfffbfed,0x3fa23fed,0xbfe2bf8e,0xbf153fd5,0xbf71bfd5,0xbff5bf8e,0xbf8e0000,0xbffb0000,0xbfd5c000,0xbec8c000,
0xbffbbfed,0x3fd5bf44,0x3ec8bf44,0x3f8e3fed,0xbec8bfb5,0xbf8e3fb5,0x3ffb3fb5,0xbfd5bfb5,0x3fd53f44,0x3ec8bfed,0x3f8e3fed,0x3ffb3f44,
0xbe49bfb5,0x3fa2bfb5,0x3fff3fb5,0x3fc63fb5,0x3ff53f8e,0xbf713fd5,0x3f153fd5,0xbfe2bf8e,0x3f713fed,0x3f15bfed,0xbfe2bf44,0x3ff53f44,
0xbfc6bec8,0xbe493ffb,0xbfa2bffb,0xbfffbec8,0x4000,0xbfb54000,0xc0000000,0xbfb50000,0xc000,0x3fb50000,0x40000000,0xbfb54000,
0x4000,0x3fb5c000,0xc0000000,0x3fb50000,0xc000,0xbfb50000,0x40000000,0x3fb5c000,0xbfa2bfb5,0x3e49bfb5,0x3fc6bfb5,0x3fffbfb5,
0x3f713fd5,0xbff53f8e,0xbfe23f8e,0x3f15bfd5,0xbf15bfed,0xbf713fed,0x3ff5bf44,0xbfe23f44,0x3e493ffb,0x3fc6bec8,0xbfff3ec8,0xbfa23ffb,
0x3ffb0000,0x3f8e0000,0xbec84000,0xbfd54000,0xbfd5bf44,0x3ffbbfed,0x3f8ebfed,0x3ec83f44,0x3f8e3fb5,0x3ec8bfb5,0xbfd53fb5,0x3ffbbfb5,
0xbec8bfed,0xbfd53f44,0x3ffbbf44,0x3f8ebfed,0xbfe23fb5,0xbff53fb5,0xbf71bfb5,0x3f15bfb5,0x3fffbec8,0xbfc63ffb,0xbe493ffb,0xbfa23ec8,
0xbfc6bf44,0x3e493f44,0x3fa2bfed,0xbfff3fed,0x3f153fd5,0x3fe2bf8e,0xbff53f8e,0xbf713fd5,0x3f44c000,0x3fedc000,0x3fed0000,0x3f440000,
0xbfed3fb5,0x3f44bfb5,0xbf44bfb5,0x3fedbfb5,0x3fed0000,0xbf440000,0xbf444000,0x3fedc000,0xbf44bfb5,0xbfed3fb5,0x3fedbfb5,0x3f44bfb5,
0x3f153fb5,0xbf713fb5,0xbff53fb5,0xbfe23fb5,0x3fa2bffb,0x3e493ec8,0x3fc63ec8,0xbfff3ffb,0xbfff3f44,0x3fa2bf44,0x3e49bfed,0xbfc63fed,
0x3f713f8e,0x3ff5bfd5,0xbfe23fd5,0xbf153f8e,0xbfd50000,0xbec80000,0x3f8ec000,0x3ffbc000,0xbec83fed,0xbf8e3f44,0xbffb3f44,0x3fd5bfed,
0x3ffbbfb5,0xbfd53fb5,0x3ec83fb5,0x3f8ebfb5,0xbf8ebf44,0xbffb3fed,0x3fd5bfed,0x3ec8bf44,0x3fffbfb5,0x3fc6bfb5,0x3e493fb5,0xbfa23fb5,
0xbf15bf8e,0x3fe2bfd5,0x3ff5bfd5,0xbf713f8e,0xbfe23fed,0x3ff5bfed,0xbf71bf44,0xbf153f44,0x3fa23ec8,0x3fffbffb,0xbfc63ffb,0xbe493ec8,
0xc0004000,0xbfb54000,0x0,0x3fb50000,0xc0004000,0x3fb50000,0x0,0x3fb5c000,0xc0004000,0x3fb5c000,0x0,0xbfb50000,
0xc0004000,0xbfb50000,0x0,0xbfb54000,0x3fc6bfb5,0x3fffbfb5,0x3fa2bfb5,0xbe49bfb5,0x3fe2bfd5,0xbf15bf8e,0x3f71bf8e,0xbff53fd5,
0x3ff5bfed,0xbfe23fed,0x3f15bf44,0x3f713f44,0x3fffbffb,0x3fa23ec8,0x3e49bec8,0x3fc6bffb,0xbec80000,0xbfd50000,0xbffb4000,0xbf8e4000,
0xbf8e3f44,0xbec83fed,0xbfd53fed,0x3ffbbf44,0xbfd53fb5,0x3ffbbfb5,0xbf8e3fb5,0xbec8bfb5,0xbffb3fed,0xbf8ebf44,0xbec83f44,0xbfd53fed,
0xbf713fb5,0x3f153fb5,0x3fe2bfb5,0x3ff5bfb5,0x3e493ec8,0x3fa2bffb,0x3fffbffb,0xbfc6bec8,0x3fa2bf44,0xbfff3f44,0x3fc6bfed,0xbe493fed,
0x3ff5bfd5,0x3f713f8e,0x3f15bf8e,0x3fe2bfd5,0x3fedc000,0x3f44c000,0xbf440000,0xbfed0000,0x3f44bfb5,0xbfed3fb5,0xbfed3fb5,0x3f443fb5,
0xbf440000,0x3fed0000,0xbfed4000,0x3f44c000,0xbfed3fb5,0xbf44bfb5,0xbf443fb5,0xbfed3fb5,0xbff53fb5,0xbfe23fb5,0xbf153fb5,0x3f713fb5,
0xbfc63ffb,0x3fffbec8,0x3fa2bec8,0x3e49bffb,0x3e493f44,0xbfc6bf44,0x3fffbfed,0xbfa23fed,0x3fe2bf8e,0x3f153fd5,0x3f71bfd5,0x3ff5bf8e,
0x3f8e0000,0x3ffb0000,0x3fd5c000,0x3ec8c000,0x3ffbbfed,0xbfd5bf44,0xbec8bf44,0xbf8e3fed,0x3ec8bfb5,0x3f8e3fb5,0xbffb3fb5,0x3fd5bfb5,
0xbfd53f44,0xbec8bfed,0xbf8e3fed,0xbffb3f44,0x3e49bfb5,0xbfa2bfb5,0xbfff3fb5,0xbfc63fb5,0xbff53f8e,0x3f713fd5,0xbf153fd5,0x3fe2bf8e,
0xbf713fed,0xbf15bfed,0x3fe2bf44,0xbff53f44,0x3fc6bec8,0x3e493ffb,0x3fa2bffb,0x3fffbec8,0x4000,0x3fb54000,0x40000000,0x3fb50000,
0xc000,0xbfb50000,0xc0000000,0x3fb54000,0x4000,0xbfb5c000,0x40000000,0xbfb50000,0xc000,0x3fb50000,0xc0000000,0xbfb5c000,
0x3fa2bfb5,0xbe49bfb5,0xbfc6bfb5,0xbfffbfb5,0xbf713fd5,0x3ff53f8e,0x3fe23f8e,0xbf15bfd5,0x3f15bfed,0x3f713fed,0xbff5bf44,0x3fe23f44,
0xbe493ffb,0xbfc6bec8,0x3fff3ec8,0x3fa23ffb,0xbffb0000,0xbf8e0000,0x3ec84000,0x3fd54000,0x3fd5bf44,0xbffbbfed,0xbf8ebfed,0xbec83f44,
0xbf8e3fb5,0xbec8bfb5,0x3fd53fb5,0xbffbbfb5,0x3ec8bfed,0x3fd53f44,0xbffbbf44,0xbf8ebfed,0x3fe23fb5,0x3ff53fb5,0x3f71bfb5,0xbf15bfb5,
0xbfffbec8,0x3fc63ffb,0x3e493ffb,0x3fa23ec8,0x3fc6bf44,0xbe493f44,0xbfa2bfed,0x3fff3fed,0xbf153fd5,0xbfe2bf8e,0x3ff53f8e,0x3f713fd5,
0xbf44c000,0xbfedc000,0xbfed0000,0xbf440000,0x3fed3fb5,0xbf44bfb5,0x3f44bfb5,0xbfedbfb5,0xbfed0000,0x3f440000,0x3f444000,0xbfedc000,
0x3f44bfb5,0x3fed3fb5,0xbfedbfb5,0xbf44bfb5,0xbf153fb5,0x3f713fb5,0x3ff53fb5,0x3fe23fb5,0xbfa2bffb,0xbe493ec8,0xbfc63ec8,0x3fff3ffb,
0x3fff3f44,0xbfa2bf44,0xbe49bfed,0x3fc63fed,0xbf713f8e,0xbff5bfd5,0x3fe23fd5,0x3f153f8e,0x3fd50000,0x3ec80000,0xbf8ec000,0xbffbc000,
0x3ec83fed,0x3f8e3f44,0x3ffb3f44,0xbfd5bfed,0xbffbbfb5,0x3fd53fb5,0xbec83fb5,0xbf8ebfb5,0x3f8ebf44,0x3ffb3fed,0xbfd5bfed,0xbec8bf44,
0xbfffbfb5,0xbfc6bfb5,0xbe493fb5,0x3fa23fb5,0x3f15bf8e,0xbfe2bfd5,0xbff5bfd5,0x3f713f8e,0x3fe23fed,0xbff5bfed,0x3f71bf44,0x3f153f44,
0xbfa23ec8,0xbfffbffb,0x3fc63ffb,0x3e493ec8,0x80003f80,0x3f800000,0x80003f80,0x3f800000,0x80003f80,0x3f800000,0x80003f80,0x3f800000,
0x80003f80,0x3f800000,0x80003f80,0x3f800000,0x80003f80,0x3f800000,0x80003f80,0x3f800000,0x80003f80,0x3f800000,0x8000bf80,0xbf800000,
0x3f353f35,0x3f35bf35,0xbf35bf35,0xbf353f35,0x3f800000,0xbf80,0xbf800000,0x3f80,0x3f35bf35,0xbf35bf35,0xbf353f35,0x3f353f35,
0x80003f80,0x3f800000,0x80003f80,0x3f800000,0x3f800000,0xbf80,0x3f800000,0xbf80,0x8000bf80,0xbf800000,0x8000bf80,0xbf800000,
0xbf800000,0x3f80,0xbf800000,0x3f80,0x80003f80,0x3f800000,0x8000bf80,0xbf800000,0x3f35bf35,0xbf35bf35,0xbf353f35,0x3f353f35,
0xbf800000,0x3f80,0x3f800000,0xbf80,0x3f353f35,0x3f35bf35,0xbf35bf35,0xbf353f35,0x80003f80,0x3f800000,0x80003f80,0x3f800000,
0x8000bf80,0xbf800000,0x8000bf80,0xbf800000,0x80003f80,0x3f800000,0x80003f80,0x3f800000,0x8000bf80,0xbf800000,0x8000bf80,0xbf800000,
0x80003f80,0x3f800000,0x8000bf80,0xbf800000,0xbf35bf35,0xbf353f35,0x3f353f35,0x3f35bf35,0x3f800000,0xbf80,0xbf800000,0x3f80,
0xbf353f35,0x3f353f35,0x3f35bf35,0xbf35bf35,0x80003f80,0x3f800000,0x80003f80,0x3f800000,0xbf800000,0x3f80,0xbf800000,0x3f80,
0x8000bf80,0xbf800000,0x8000bf80,0xbf800000,0x3f800000,0xbf80,0x3f800000,0xbf80,0x80003f80,0x3f800000,0x8000bf80,0xbf800000,
0xbf353f35,0x3f353f35,0x3f35bf35,0xbf35bf35,0xbf800000,0x3f80,0x3f800000,0xbf80,0xbf35bf35,0xbf353f35,0x3f353f35,0x3f35bf35,
0x3f803f80,0x80008000,0x80008000,0xbf80bf80,0x3f803f80,0x80008000,0x80008000,0xbf80bf80,0x3f803f80,0x80008000,0x80008000,0xbf80bf80,
0x3f803f80,0x80008000,0x80008000,0xbf80bf80,0x3f353f80,0x3f358000,0x3f358000,0xbf35bf80,0xbf350000,0x3f353f80,0x3f353f80,0x3f358000,
0xbf35bf80,0xbf358000,0xbf358000,0x3f353f80,0x3f350000,0xbf35bf80,0xbf35bf80,0xbf358000,0x3f80,0x3f808000,0x3f808000,0x8000bf80,
0xbf80,0xbf808000,0xbf808000,0x80003f80,0x3f80,0x3f808000,0x3f808000,0x8000bf80,0xbf80,0xbf808000,0xbf808000,0x80003f80,
0xbf353f80,0x3f358000,0x3f358000,0x3f35bf80,0x3f350000,0x3f35bf80,0x3f35bf80,0xbf358000,0x3f35bf80,0xbf358000,0xbf358000,0xbf353f80,
0xbf350000,0xbf353f80,0xbf353f80,0x3f358000,0xbf803f80,0x80008000,0x80008000,0x3f80bf80,0xbf803f80,0x80008000,0x80008000,0x3f80bf80,
0xbf803f80,0x80008000,0x80008000,0x3f80bf80,0xbf803f80,0x80008000,0x80008000,0x3f80bf80,0xbf353f80,0xbf358000,0xbf358000,0x3f35bf80,
0x3f350000,0xbf353f80,0xbf353f80,0xbf358000,0x3f35bf80,0x3f358000,0x3f358000,0xbf353f80,0xbf350000,0x3f35bf80,0x3f35bf80,0x3f358000,
0x3f80,0xbf808000,0xbf808000,0x8000bf80,0xbf80,0x3f808000,0x3f808000,0x80003f80,0x3f80,0xbf808000,0xbf808000,0x8000bf80,
0xbf80,0x3f808000,0x3f808000,0x80003f80,0x3f353f80,0xbf358000,0xbf358000,0xbf35bf80,0xbf350000,0xbf35bf80,0xbf35bf80,0x3f358000,
0xbf35bf80,0x3f358000,0x3f358000,0x3f353f80,0x3f350000,0x3f353f80,0x3f353f80,0xbf358000,0x3f800000,0x0,0x3f800000,0x0,
0x3f800000,0x0,0x3f800000,0x0,0x3f800000,0x0,0x3f800000,0x0,0x3f800000,0x0,0x3f800000,0x0,
0x3f800000,0x0,0x3f7fb10f,0xbd48fb30,0x3f7ec46d,0xbdc8bd36,0x3f7d3aac,0xbe164083,0x3f7b14be,0xbe47c5c2,0x3f7853f8,0xbe78cfcc,
0x3f74fa0b,0xbe94a031,0x3f710908,0xbeac7cd4,0x3f800000,0x0,0x3f7ec46d,0xbdc8bd36,0x3f7b14be,0xbe47c5c2,0x3f74fa0b,0xbe94a031,
0x3f6c835e,0xbec3ef15,0x3f61c598,0xbef15aea,0x3f54db31,0xbf0e39da,0x3f45e403,0xbf226799,0x3f800000,0x0,0x3f7d3aac,0xbe164083,
0x3f74fa0b,0xbe94a031,0x3f676bd8,0xbedae880,0x3f54db31,0xbf0e39da,0x3f3daef9,0xbf2beb4a,0x3f226799,0xbf45e403,0x3f039c3d,0xbf5b941a,
0x3f800000,0x0,0x3f7b14be,0xbe47c5c2,0x3f6c835e,0xbec3ef15,0x3f54db31,0xbf0e39da,0x3f3504f3,0xbf3504f3,0x3f0e39da,0xbf54db31,
0x3ec3ef15,0xbf6c835e,0x3e47c5c2,0xbf7b14be,0x3f800000,0x0,0x3f7853f8,0xbe78cfcc,0x3f61c598,0xbef15aea,0x3f3daef9,0xbf2beb4a,
0x3f0e39da,0xbf54db31,0x3eac7cd4,0xbf710908,0x3dc8bd36,0xbf7ec46d,0xbe164083,0xbf7d3aac,0x3f800000,0x0,0x3f74fa0b,0xbe94a031,
0x3f54db31,0xbf0e39da,0x3f226799,0xbf45e403,0x3ec3ef15,0xbf6c835e,0x3dc8bd36,0xbf7ec46d,0xbe47c5c2,0xbf7b14be,0xbef15aea,0xbf61c598,
0x3f800000,0x0,0x3f710908,0xbeac7cd4,0x3f45e403,0xbf226799,0x3f039c3d,0xbf5b941a,0x3e47c5c2,0xbf7b14be,0xbe164083,0xbf7d3aac,
0xbef15aea,0xbf61c598,0xbf3daef9,0xbf2beb4a,0x3f800000,0x0,0x3f800000,0x0,0x3f800000,0x0,0x3f800000,0x0,
0x3f800000,0x0,0x3f800000,0x0,0x3f800000,0x0,0x3f800000,0x0,0x3f6c835e,0xbec3ef15,0x3f676bd8,0xbedae880,
0x3f61c598,0xbef15aea,0x3f5b941a,0xbf039c3d,0x3f54db31,0xbf0e39da,0x3f4d9f02,0xbf187fc0,0x3f45e403,0xbf226799,0x3f3daef9,0xbf2beb4a,
0x3f3504f3,0xbf3504f3,0x3f226799,0xbf45e403,0x3f0e39da,0xbf54db31,0x3ef15aea,0xbf61c598,0x3ec3ef15,0xbf6c835e,0x3e94a031,0xbf74fa0b,
0x3e47c5c2,0xbf7b14be,0x3dc8bd36,0xbf7ec46d,0x3ec3ef15,0xbf6c835e,0x3e78cfcc,0xbf7853f8,0x3dc8bd36,0xbf7ec46d,0xbd48fb30,0xbf7fb10f,
0xbe47c5c2,0xbf7b14be,0xbeac7cd4,0xbf710908,0xbef15aea,0xbf61c598,0xbf187fc0,0xbf4d9f02,0x0,0xbf800000,0xbe47c5c2,0xbf7b14be,
0xbec3ef15,0xbf6c835e,0xbf0e39da,0xbf54db31,0xbf3504f3,0xbf3504f3,0xbf54db31,0xbf0e39da,0xbf6c835e,0xbec3ef15,0xbf7b14be,0xbe47c5c2,
0xbec3ef15,0xbf6c835e,0xbf187fc0,0xbf4d9f02,0xbf45e403,0xbf226799,0xbf676bd8,0xbedae880,0xbf7b14be,0xbe47c5c2,0xbf7fb10f,0x3d48fb30,
0xbf74fa0b,0x3e94a031,0xbf5b941a,0x3f039c3d,0xbf3504f3,0xbf3504f3,0xbf61c598,0xbef15aea,0xbf7b14be,0xbe47c5c2,0xbf7ec46d,0x3dc8bd36,
0xbf6c835e,0x3ec3ef15,0xbf45e403,0x3f226799,0xbf0e39da,0x3f54db31,0xbe94a031,0x3f74fa0b,0xbf6c835e,0xbec3ef15,0xbf7fb10f,0xbd48fb30,
0xbf74fa0b,0x3e94a031,0xbf4d9f02,0x3f187fc0,0xbf0e39da,0x3f54db31,0xbe78cfcc,0x3f7853f8,0x3dc8bd36,0x3f7ec46d,0x3edae880,0x3f676bd8,
0x80003f80,0x3f800000,0x3f800000,0xbf80,0x3ec43f6d,0x3f6dbec4,0x3f6dbec4,0xbec4bf6d,0x3f353f35,0x3f35bf35,0x3f35bf35,0xbf35bf35,
0x3f6d3ec4,0x3ec4bf6d,0x3ec4bf6d,0xbf6dbec4,0x80003f80,0x3f800000,0xbf800000,0x3f80,0x3f6d3ec4,0x3ec4bf6d,0xbec43f6d,0x3f6d3ec4,
0x3f35bf35,0xbf35bf35,0x3f353f35,0x3f35bf35,0xbec4bf6d,0xbf6d3ec4,0x3f6dbec4,0xbec4bf6d,0x80003f80,0x3f800000,0x3f800000,0xbf80,
0x3f6dbec4,0xbec4bf6d,0xbec4bf6d,0xbf6d3ec4,0xbf35bf35,0xbf353f35,0xbf353f35,0x3f353f35,0xbec43f6d,0x3f6d3ec4,0x3f6d3ec4,0x3ec4bf6d,
0x80003f80,0x3f800000,0xbf800000,0x3f80,0x3ec4bf6d,0xbf6dbec4,0x3f6d3ec4,0x3ec4bf6d,0xbf353f35,0x3f353f35,0xbf35bf35,0xbf353f35,
0x3f6dbec4,0xbec4bf6d,0x3ec43f6d,0x3f6dbec4,0x80003f80,0x3f800000,0x3f800000,0xbf80,0xbec4bf6d,0xbf6d3ec4,0xbf6d3ec4,0x3ec43f6d,
0x3f353f35,0x3f35bf35,0x3f35bf35,0xbf35bf35,0xbf6dbec4,0xbec43f6d,0xbec43f6d,0x3f6d3ec4,0x80003f80,0x3f800000,0xbf800000,0x3f80,
0xbf6dbec4,0xbec43f6d,0x3ec4bf6d,0xbf6dbec4,0x3f35bf35,0xbf35bf35,0x3f353f35,0x3f35bf35,0x3ec43f6d,0x3f6dbec4,0xbf6d3ec4,0x3ec43f6d,
0x80003f80,0x3f800000,0x3f800000,0xbf80,0xbf6d3ec4,0x3ec43f6d,0x3ec43f6d,0x3f6dbec4,0xbf35bf35,0xbf353f35,0xbf353f35,0x3f353f35,
0x3ec4bf6d,0xbf6dbec4,0xbf6dbec4,0xbec43f6d,0x80003f80,0x3f800000,0xbf800000,0x3f80,0xbec43f6d,0x3f6d3ec4,0xbf6dbec4,0xbec43f6d,
0xbf353f35,0x3f353f35,0xbf35bf35,0xbf353f35,0xbf6d3ec4,0x3ec43f6d,0xbec4bf6d,0xbf6d3ec4,0x3f803f80,0x80008000,0x80008000,0xbf80bf80,
0x3f803f80,0x80008000,0x80008000,0xbf80bf80,0x3f803f80,0x80008000,0x80008000,0xbf80bf80,0x3f803f80,0x80008000,0x80008000,0xbf80bf80,
0x3ec43f6d,0x3f6d3ec4,0x3f6d3ec4,0xbec4bf6d,0xbf6dbec4,0x3ec43f6d,0x3ec43f6d,0x3f6d3ec4,0xbec4bf6d,0xbf6dbec4,0xbf6dbec4,0x3ec43f6d,
0x3f6d3ec4,0xbec4bf6d,0xbec4bf6d,0xbf6dbec4,0xbf353f35,0x3f353f35,0x3f353f35,0x3f35bf35,0x3f35bf35,0xbf35bf35,0xbf35bf35,0xbf353f35,
0xbf353f35,0x3f353f35,0x3f353f35,0x3f35bf35,0x3f35bf35,0xbf35bf35,0xbf35bf35,0xbf353f35,0xbf6d3ec4,0xbec43f6d,0xbec43f6d,0x3f6dbec4,
0xbec43f6d,0x3f6dbec4,0x3f6dbec4,0x3ec4bf6d,0x3f6dbec4,0x3ec4bf6d,0x3ec4bf6d,0xbf6d3ec4,0x3ec4bf6d,0xbf6d3ec4,0xbf6d3ec4,0xbec43f6d,
0x0,0xbf803f80,0xbf803f80,0x80008000,0x0,0xbf803f80,0xbf803f80,0x80008000,0x0,0xbf803f80,0xbf803f80,0x80008000,
0x0,0xbf803f80,0xbf803f80,0x80008000,0x3f6dbec4,0xbec43f6d,0xbec43f6d,0xbf6d3ec4,0x3ec4bf6d,0x3f6dbec4,0x3f6dbec4,0xbec43f6d,
0xbf6d3ec4,0x3ec4bf6d,0x3ec4bf6d,0x3f6dbec4,0xbec43f6d,0xbf6d3ec4,0xbf6d3ec4,0x3ec4bf6d,0x3f35bf35,0x3f353f35,0x3f353f35,0xbf353f35,
0xbf353f35,0xbf35bf35,0xbf35bf35,0x3f35bf35,0x3f35bf35,0x3f353f35,0x3f353f35,0xbf353f35,0xbf353f35,0xbf35bf35,0xbf35bf35,0x3f35bf35,
0xbec4bf6d,0x3f6d3ec4,0x3f6d3ec4,0x3ec43f6d,0x3f6d3ec4,0x3ec43f6d,0x3ec43f6d,0xbf6dbec4,0x3ec43f6d,0xbf6dbec4,0xbf6dbec4,0xbec4bf6d,
0xbf6dbec4,0xbec4bf6d,0xbec4bf6d,0x3f6d3ec4,0x3f800000,0x0,0x3f7fec43,0xbcc90ab0,0x3f7fb10f,0xbd48fb30,0x3f7f4e6d,0xbd96a905,
0x3f7ec46d,0xbdc8bd36,0x3f7e1324,0xbdfab273,0x3f7d3aac,0xbe164083,0x3f7c3b28,0xbe2f10a2,0x3f800000,0x0,0x3f7f4e6d,0xbd96a905,
0x3f7d3aac,0xbe164083,0x3f79c79d,0xbe605c13,0x3f74fa0b,0xbe94a031,0x3f6ed89e,0xbeb8442a,0x3f676bd8,0xbedae880,0x3f5ebe05,0xbefc5d27,
0x3f800000,0x0,0x3f7e1324,0xbdfab273,0x3f7853f8,0xbe78cfcc,0x3f6ed89e,0xbeb8442a,0x3f61c598,0xbef15aea,0x3f514d3d,0xbf13682a,
0x3f3daef9,0xbf2beb4a,0x3f273656,0xbf41d870,0x3f800000,0x0,0x3f7c3b28,0xbe2f10a2,0x3f710908,0xbeac7cd4,0x3f5ebe05,0xbefc5d27,
0x3f45e403,0xbf226799,0x3f273656,0xbf41d870,0x3f039c3d,0xbf5b941a,0x3eb8442a,0xbf6ed89e,0x3f800000,0x0,0x3f79c79d,0xbe605c13,
0x3f676bd8,0xbedae880,0x3f49d112,0xbf1d7fd1,0x3f226799,0xbf45e403,0x3ee63375,0xbf64aa59,0x3e78cfcc,0xbf7853f8,0x3cc90ab0,0xbf7fec43,
0x3f800000,0x0,0x3f76ba07,0xbe888e93,0x3f5b941a,0xbf039c3d,0x3f3085bb,0xbf396842,0x3ef15aea,0xbf61c598,0x3e605c13,0xbf79c79d,
0xbd48fb30,0xbf7fb10f,0xbea09ae5,0xbf731447,0x3f800000,0x0,0x3f731447,0xbea09ae5,0x3f4d9f02,0xbf187fc0,0x3f13682a,0xbf514d3d,
0x3e94a031,0xbf74fa0b,0xbcc90ab0,0xbf7fec43,0xbeac7cd4,0xbf710908,0xbf1d7fd1,0xbf49d112,0x3f800000,0x0,0x3f6ed89e,0xbeb8442a,
0x3f3daef9,0xbf2beb4a,0x3ee63375,0xbf64aa59,0x3dc8bd36,0xbf7ec46d,0xbe888e93,0xbf76ba07,0xbf187fc0,0xbf4d9f02,0xbf584853,0xbf08f59b,
0x3f7b14be,0xbe47c5c2,0x3f79c79d,0xbe605c13,0x3f7853f8,0xbe78cfcc,0x3f76ba07,0xbe888e93,0x3f74fa0b,0xbe94a031,0x3f731447,0xbea09ae5,
0x3f710908,0xbeac7cd4,0x3f6ed89e,0xbeb8442a,0x3f54db31,0xbf0e39da,0x3f49d112,0xbf1d7fd1,0x3f3daef9,0xbf2beb4a,0x3f3085bb,0xbf396842,
0x3f226799,0xbf45e403,0x3f13682a,0xbf514d3d,0x3f039c3d,0xbf5b941a,0x3ee63375,0xbf64aa59,0x3f0e39da,0xbf54db31,0x3ee63375,0xbf64aa59,
0x3eac7cd4,0xbf710908,0x3e605c13,0xbf79c79d,0x3dc8bd36,0xbf7ec46d,0xbcc90ab0,0xbf7fec43,0xbe164083,0xbf7d3aac,0xbe888e93,0xbf76ba07,
0x3e47c5c2,0xbf7b14be,0x3cc90ab0,0xbf7fec43,0xbe164083,0xbf7d3aac,0xbea09ae5,0xbf731447,0xbef15aea,0xbf61c598,0xbf1d7fd1,0xbf49d112,
0xbf3daef9,0xbf2beb4a,0xbf584853,0xbf08f59b,0xbe47c5c2,0xbf7b14be,0xbecf7bca,0xbf6a09a7,0xbf187fc0,0xbf4d9f02,0xbf41d870,0xbf273656,
0xbf61c598,0xbef15aea,0xbf76ba07,0xbe888e93,0xbf7fb10f,0xbd48fb30,0xbf7c3b28,0x3e2f10a2,0xbf0e39da,0xbf54db31,0xbf41d870,0xbf273656,
0xbf676bd8,0xbedae880,0xbf7c3b28,0xbe2f10a2,0xbf7ec46d,0x3dc8bd36,0xbf6ed89e,0x3eb8442a,0xbf4d9f02,0x3f187fc0,0xbf1d7fd1,0x3f49d112,
0xbf54db31,0xbf0e39da,0xbf76ba07,0xbe888e93,0xbf7fb10f,0x3d48fb30,0xbf6ed89e,0x3eb8442a,0xbf45e403,0x3f226799,0xbf08f59b,0x3f584853,
0xbe78cfcc,0x3f7853f8,0x3d96a905,0x3f7f4e6d,0xbf7b14be,0xbe47c5c2,0xbf7c3b28,0x3e2f10a2,0xbf5b941a,0x3f039c3d,0xbf1d7fd1,0x3f49d112,
0xbe94a031,0x3f74fa0b,0x3d96a905,0x3f7f4e6d,0x3edae880,0x3f676bd8,0x3f396842,0x3f3085bb,0x80003f80,0x80003f80,0x80003f80,0x80003f80,
0x80003f80,0x80003f80,0x80003f80,0x80003f80,0x80003f80,0x80003f80,0x80003f80,0x80003f80,0x80003f80,0x80003f80,0x80003f80,0x80003f80,
0x3f800000,0x3f800000,0x3f800000,0x3f800000,0x3f800000,0x3f800000,0x3f800000,0x3f800000,0x3f800000,0x3f800000,0x3f800000,0x3f800000,
0x3f800000,0x3f800000,0x3f800000,0x3f800000,0x80003f80,0x3f353f35,0x80003f80,0x3f353f35,0x3f800000,0x3f35bf35,0x3f800000,0x3f35bf35,
0x8000bf80,0xbf35bf35,0x8000bf80,0xbf35bf35,0xbf800000,0xbf353f35,0xbf800000,0xbf353f35,0x3f800000,0x3f35bf35,0x3f800000,0x3f35bf35,
0xbf80,0xbf35bf35,0xbf80,0xbf35bf35,0xbf800000,0xbf353f35,0xbf800000,0xbf353f35,0x3f80,0x3f353f35,0x3f80,0x3f353f35,
0x80003f80,0x3f800000,0x80003f80,0x3f800000,0x8000bf80,0xbf800000,0x8000bf80,0xbf800000,0x80003f80,0x3f800000,0x80003f80,0x3f800000,
0x8000bf80,0xbf800000,0x8000bf80,0xbf800000,0x3f800000,0xbf80,0x3f800000,0xbf80,0xbf800000,0x3f80,0xbf800000,0x3f80,
0x3f800000,0xbf80,0x3f800000,0xbf80,0xbf800000,0x3f80,0xbf800000,0x3f80,0x80003f80,0x3f35bf35,0x80003f80,0x3f35bf35,
0xbf800000,0x3f353f35,0xbf800000,0x3f353f35,0x8000bf80,0xbf353f35,0x8000bf80,0xbf353f35,0x3f800000,0xbf35bf35,0x3f800000,0xbf35bf35,
0x3f800000,0xbf35bf35,0x3f800000,0xbf35bf35,0x3f80,0x3f35bf35,0x3f80,0x3f35bf35,0xbf800000,0x3f353f35,0xbf800000,0x3f353f35,
0xbf80,0xbf353f35,0xbf80,0xbf353f35,0x80003f80,0x3ec43f6d,0x8000bf80,0xbec4bf6d,0x3f353f35,0x3f6d3ec4,0xbf35bf35,0xbf6dbec4,
0x3f800000,0x3f6dbec4,0xbf800000,0xbf6d3ec4,0x3f35bf35,0x3ec4bf6d,0xbf353f35,0xbec43f6d,0x3f800000,0x3f6dbec4,0xbf800000,0xbf6d3ec4,
0x3f35bf35,0x3ec4bf6d,0xbf353f35,0xbec43f6d,0xbf80,0xbec4bf6d,0x3f80,0x3ec43f6d,0xbf35bf35,0xbf6dbec4,0x3f353f35,0x3f6d3ec4,
0x80003f80,0x3f6d3ec4,0x8000bf80,0xbf6dbec4,0x3f35bf35,0xbec4bf6d,0xbf353f35,0x3ec43f6d,0xbf800000,0xbec43f6d,0x3f800000,0x3ec4bf6d,
0x3f353f35,0x3f6dbec4,0xbf35bf35,0xbf6d3ec4,0x3f800000,0x3ec4bf6d,0xbf800000,0xbec43f6d,0xbf35bf35,0xbf6d3ec4,0x3f353f35,0x3f6dbec4,
0x3f80,0x3f6d3ec4,0xbf80,0xbf6dbec4,0x3f35bf35,0xbec4bf6d,0xbf353f35,0x3ec43f6d,0x80003f80,0x3f6dbec4,0x8000bf80,0xbf6d3ec4,
0xbf35bf35,0xbec43f6d,0x3f353f35,0x3ec4bf6d,0x3f800000,0xbec4bf6d,0xbf800000,0x3ec43f6d,0xbf353f35,0x3f6d3ec4,0x3f35bf35,0xbf6dbec4,
0x3f800000,0xbec4bf6d,0xbf800000,0x3ec43f6d,0xbf353f35,0x3f6d3ec4,0x3f35bf35,0xbf6dbec4,0xbf80,0xbf6d3ec4,0x3f80,0x3f6dbec4,
0x3f353f35,0x3ec4bf6d,0xbf35bf35,0xbec43f6d,0x80003f80,0x3ec4bf6d,0x8000bf80,0xbec43f6d,0xbf353f35,0x3f6dbec4,0x3f35bf35,0xbf6d3ec4,
0xbf800000,0x3f6d3ec4,0x3f800000,0xbf6dbec4,0xbf35bf35,0x3ec43f6d,0x3f353f35,0xbec4bf6d,0x3f800000,0xbf6dbec4,0xbf800000,0x3f6d3ec4,
0x3f353f35,0xbec4bf6d,0xbf35bf35,0x3ec43f6d,0x3f80,0x3ec4bf6d,0xbf80,0xbec43f6d,0xbf353f35,0x3f6dbec4,0x3f35bf35,0xbf6d3ec4,
0x80003f80,0x8000bf80,0x80003f80,0x8000bf80,0x80003f80,0x8000bf80,0x80003f80,0x8000bf80,0x80003f80,0x8000bf80,0x80003f80,0x8000bf80,
0x80003f80,0x8000bf80,0x80003f80,0x8000bf80,0x3f800000,0xbf800000,0x3f800000,0xbf800000,0x3f800000,0xbf800000,0x3f800000,0xbf800000,
0x3f800000,0xbf800000,0x3f800000,0xbf800000,0x3f800000,0xbf800000,0x3f800000,0xbf800000,0x80003f80,0xbf35bf35,0x80003f80,0xbf35bf35,
0x3f800000,0xbf353f35,0x3f800000,0xbf353f35,0x8000bf80,0x3f353f35,0x8000bf80,0x3f353f35,0xbf800000,0x3f35bf35,0xbf800000,0x3f35bf35,
0x3f800000,0xbf353f35,0x3f800000,0xbf353f35,0xbf80,0x3f353f35,0xbf80,0x3f353f35,0xbf800000,0x3f35bf35,0xbf800000,0x3f35bf35,
0x3f80,0xbf35bf35,0x3f80,0xbf35bf35,0x80003f80,0xbf800000,0x80003f80,0xbf800000,0x8000bf80,0x3f800000,0x8000bf80,0x3f800000,
0x80003f80,0xbf800000,0x80003f80,0xbf800000,0x8000bf80,0x3f800000,0x8000bf80,0x3f800000,0x3f800000,0x3f80,0x3f800000,0x3f80,
0xbf800000,0xbf80,0xbf800000,0xbf80,0x3f800000,0x3f80,0x3f800000,0x3f80,0xbf800000,0xbf80,0xbf800000,0xbf80,
0x80003f80,0xbf353f35,0x80003f80,0xbf353f35,0xbf800000,0xbf35bf35,0xbf800000,0xbf35bf35,0x8000bf80,0x3f35bf35,0x8000bf80,0x3f35bf35,
0x3f800000,0x3f353f35,0x3f800000,0x3f353f35,0x3f800000,0x3f353f35,0x3f800000,0x3f353f35,0x3f80,0xbf353f35,0x3f80,0xbf353f35,
0xbf800000,0xbf35bf35,0xbf800000,0xbf35bf35,0xbf80,0x3f35bf35,0xbf80,0x3f35bf35,0x80003f80,0xbec4bf6d,0x8000bf80,0x3ec43f6d,
0x3f353f35,0xbf6dbec4,0xbf35bf35,0x3f6d3ec4,0x3f800000,0xbf6d3ec4,0xbf800000,0x3f6dbec4,0x3f35bf35,0xbec43f6d,0xbf353f35,0x3ec4bf6d,
0x3f800000,0xbf6d3ec4,0xbf800000,0x3f6dbec4,0x3f35bf35,0xbec43f6d,0xbf353f35,0x3ec4bf6d,0xbf80,0x3ec43f6d,0x3f80,0xbec4bf6d,
0xbf35bf35,0x3f6d3ec4,0x3f353f35,0xbf6dbec4,0x80003f80,0xbf6dbec4,0x8000bf80,0x3f6d3ec4,0x3f35bf35,0x3ec43f6d,0xbf353f35,0xbec4bf6d,
0xbf800000,0x3ec4bf6d,0x3f800000,0xbec43f6d,0x3f353f35,0xbf6d3ec4,0xbf35bf35,0x3f6dbec4,0x3f800000,0xbec43f6d,0xbf800000,0x3ec4bf6d,
0xbf35bf35,0x3f6dbec4,0x3f353f35,0xbf6d3ec4,0x3f80,0xbf6dbec4,0xbf80,0x3f6d3ec4,0x3f35bf35,0x3ec43f6d,0xbf353f35,0xbec4bf6d,
0x80003f80,0xbf6d3ec4,0x8000bf80,0x3f6dbec4,0xbf35bf35,0x3ec4bf6d,0x3f353f35,0xbec43f6d,0x3f800000,0x3ec43f6d,0xbf800000,0xbec4bf6d,
0xbf353f35,0xbf6dbec4,0x3f35bf35,0x3f6d3ec4,0x3f800000,0x3ec43f6d,0xbf800000,0xbec4bf6d,0xbf353f35,0xbf6dbec4,0x3f35bf35,0x3f6d3ec4,
0xbf80,0x3f6dbec4,0x3f80,0xbf6d3ec4,0x3f353f35,0xbec43f6d,0xbf35bf35,0x3ec4bf6d,0x80003f80,0xbec43f6d,0x8000bf80,0x3ec4bf6d,
0xbf353f35,0xbf6d3ec4,0x3f35bf35,0x3f6dbec4,0xbf800000,0xbf6dbec4,0x3f800000,0x3f6d3ec4,0xbf35bf35,0xbec4bf6d,0x3f353f35,0x3ec43f6d,
0x3f800000,0x3f6d3ec4,0xbf800000,0xbf6dbec4,0x3f353f35,0x3ec43f6d,0xbf35bf35,0xbec4bf6d,0x3f80,0xbec43f6d,0xbf80,0x3ec4bf6d,
0xbf353f35,0xbf6d3ec4,0x3f35bf35,0x3f6dbec4,
};
constexpr int TB_F = 0, TB_E = 512, TB_P2 = 1024;

enum { C_EP = 0, C_Z1 = 32, C_Z2 = 96, C_H3 = 128, C_U = 160, C_TOTAL = 256 };
struct Scratch {
  unsigned cnt[C_TOTAL];
  uint32_t mod[6 * D_ + 384];
  uint32_t z1[120 * 5120];
  uint32_t z2[128 * 4800];
  uint32_t x1[S_ * D_ / 2];
  uint8_t h3[32 * 18 * 4096];
  uint8_t u[72 * D_ * 128];
  uint4 part[128 * 1152];
};
__device__ __align__(1024) Scratch g_s;

#define PF2 8
#define PF2K 16
#define HOLDA 3
#define GOAT 1
#define HOLD1 0
#define XPOS 0
#define HW bulk_commit_wait
#define H3W 0
#define X1K 10
#define PEEK 1
#define NG1 2

#define FAILCNT(k) do {} while (0)
#define CK(k) do {} while (0)
#define CKX(k) do {} while (0)
#define TS(k) do {} while (0)
#define TSC(k) do {} while (0)
struct Maps { CUtensorMap w1a, w1b, w2, x1, out, z1, z2, h3, wf[4], wm; };
struct Params {
  const __nv_bfloat16 *x, *c, *wmod;
  Scratch* s;
  const uint4* tab;
  const __nv_bfloat16 *wr, *wi, *w1, *w2, *b1, *b2;
};

__device__ __forceinline__ uint32_t smem_u32(const void* p) { return (uint32_t)__cvta_generic_to_shared(p); }
__device__ __forceinline__ void mbar_init(uint32_t b, int c) { asm volatile("mbarrier.init.shared::cta.b64 [%0], %1;" ::"r"(b), "r"(c)); }
__device__ __forceinline__ void mbar_expect(uint32_t b, int bytes) { asm volatile("mbarrier.arrive.expect_tx.shared::cta.b64 _, [%0], %1;" ::"r"(b), "r"(bytes) : "memory"); }
__device__ __forceinline__ void mbar_arrive(uint32_t b) { asm volatile("mbarrier.arrive.shared::cta.b64 _, [%0];" ::"r"(b) : "memory"); }
#define MBAR_WAIT(SEM)                                                                                                         \
  asm volatile("{\n.reg .pred p;\n.reg .u32 it;\nmov.u32 it, 0;\nW:\nmbarrier.try_wait.parity" SEM ".shared::cta.b64 p, [%0], %1;\n" \
               "@p bra.uni D;\nadd.u32 it, it, 1;\nsetp.lt.u32 p, it, 0x400000;\n@p bra.uni W;\ntrap;\nD:\n}" ::"r"(b), "r"(ph) : "memory")
__device__ __forceinline__ void mbar_wait(uint32_t b, int ph) { MBAR_WAIT(""); }
__device__ __forceinline__ uint32_t mbar_test(uint32_t b, int ph) {
  uint32_t ok;
  asm volatile("{\n.reg .pred p;\nmbarrier.test_wait.parity.shared::cta.b64 p, [%1], %2;\nselp.u32 %0, 1, 0, p;\n}\n" : "=r"(ok) : "r"(b), "r"(ph) : "memory");
  return ok;
}
__device__ __forceinline__ void tma2d(uint32_t dst, const CUtensorMap* m, int c0, int c1, uint32_t bar) {
  asm volatile("cp.async.bulk.tensor.2d.shared::cluster.global.mbarrier::complete_tx::bytes [%0], [%1, {%3, %4}], [%2];" ::"r"(dst), "l"(m), "r"(bar), "r"(c0), "r"(c1) : "memory");
}
__device__ __forceinline__ uint64_t pol_ef() { uint64_t p; asm("createpolicy.fractional.L2::evict_first.b64 %0, 1.0;" : "=l"(p)); return p; }
__device__ __forceinline__ void tma3d_ef(uint32_t dst, const CUtensorMap* m, int c1, int c2, uint32_t bar) {
  asm volatile("cp.async.bulk.tensor.3d.shared::cluster.global.mbarrier::complete_tx::bytes.L2::cache_hint [%0], [%1, {%3, %4, %5}], [%2], %6;" ::"r"(dst), "l"(m), "r"(bar), "r"(0), "r"(c1), "r"(c2), "l"(pol_ef()) : "memory");
}
__device__ __forceinline__ void tma4d_ef(uint32_t dst, const CUtensorMap* m, int c1, int c2, int c3, uint32_t bar) {
  asm volatile("cp.async.bulk.tensor.4d.shared::cluster.global.mbarrier::complete_tx::bytes.L2::cache_hint [%0], [%1, {%3, %7, %4, %5}], [%2], %6;" ::"r"(dst), "l"(m), "r"(bar), "r"(0), "r"(c2), "r"(c3), "l"(pol_ef()), "r"(c1) : "memory");
}
__device__ __forceinline__ void bulk_ld(uint32_t dst, const void* src, int bytes, uint32_t bar) {
  asm volatile("cp.async.bulk.shared::cluster.global.mbarrier::complete_tx::bytes [%0], [%1], %2, [%3];" ::"r"(dst), "l"(src), "r"(bytes), "r"(bar) : "memory");
}
__device__ __forceinline__ void bulk_st(void* dst, uint32_t src, int bytes) {
  asm volatile("cp.async.bulk.global.shared::cta.bulk_group [%0], [%1], %2;" ::"l"(dst), "r"(src), "r"(bytes) : "memory");
}
__device__ __forceinline__ void tma_st2d(const CUtensorMap* m, uint32_t src, int c0, int c1) {
  asm volatile("cp.async.bulk.tensor.2d.global.shared::cta.bulk_group [%0, {%2, %3}], [%1];" ::"l"(m), "r"(src), "r"(c0), "r"(c1) : "memory");
}
__device__ __forceinline__ void tma_st3d(const CUtensorMap* m, uint32_t src, int c0, int c1, int c2) {
  asm volatile("cp.async.bulk.tensor.3d.global.shared::cta.bulk_group [%0, {%2, %3, %4}], [%1];" ::"l"(m), "r"(src), "r"(c0), "r"(c1), "r"(c2) : "memory");
}
__device__ __forceinline__ void bulk_commit_wait_read() {
  asm volatile("cp.async.bulk.commit_group;" ::: "memory");
  asm volatile("cp.async.bulk.wait_group.read 0;" ::: "memory");
}
__device__ __forceinline__ void bulk_commit_wait() {
  asm volatile("cp.async.bulk.commit_group;" ::: "memory");
  asm volatile("cp.async.bulk.wait_group 0;" ::: "memory");
}
__device__ __forceinline__ void prefetch_l2(const void* p, int bytes) {
  asm volatile("cp.async.bulk.prefetch.L2.global [%0], %1;" ::"l"(p), "r"(bytes) : "memory");
}
__device__ __forceinline__ void wg_fence() { asm volatile("wgmma.fence.sync.aligned;" ::: "memory"); }
__device__ __forceinline__ void wg_commit() { asm volatile("wgmma.commit_group.sync.aligned;" ::: "memory"); }
template <int N> __device__ __forceinline__ void wg_wait() { asm volatile("wgmma.wait_group.sync.aligned %0;" ::"n"(N) : "memory"); }
template <int N> __device__ __forceinline__ void reg_fence(float (&d)[N]) {
#pragma unroll
  for (int i = 0; i < N; i++) asm volatile("" : "+f"(d[i])::"memory");
}
__device__ __forceinline__ void fence_async_smem() { asm volatile("fence.proxy.async.shared::cta;" ::: "memory"); }
__device__ __forceinline__ void fence_async_glb() { asm volatile("fence.proxy.async.global;" ::: "memory"); }
__device__ __forceinline__ uint32_t ld_rlx(const void* p) { uint32_t v; asm volatile("ld.relaxed.gpu.global.b32 %0, [%1];" : "=r"(v) : "l"(p) : "memory"); return v; }
__device__ __forceinline__ uint2 ld_rlx2(const void* p) { uint2 v; asm volatile("ld.relaxed.gpu.global.v2.b32 {%0,%1}, [%2];" : "=r"(v.x), "=r"(v.y) : "l"(p) : "memory"); return v; }
__device__ __forceinline__ uint4 ld_rlx4(const void* p) { uint4 v; asm volatile("ld.relaxed.gpu.global.v4.b32 {%0,%1,%2,%3}, [%4];" : "=r"(v.x), "=r"(v.y), "=r"(v.z), "=r"(v.w) : "l"(p) : "memory"); return v; }
__device__ __forceinline__ uint32_t ld_nc(const void* p) { uint32_t v; asm volatile("ld.global.nc.L1::no_allocate.b32 %0, [%1];" : "=r"(v) : "l"(p) : "memory"); return v; }
__device__ __forceinline__ uint32_t lds(uint32_t a) { uint32_t v; asm volatile("ld.shared.b32 %0, [%1];" : "=r"(v) : "r"(a) : "memory"); return v; }
__device__ __forceinline__ uint2 lds2(uint32_t a) { uint2 v; asm volatile("ld.shared.v2.b32 {%0,%1}, [%2];" : "=r"(v.x), "=r"(v.y) : "r"(a) : "memory"); return v; }
__device__ __forceinline__ uint4 lds4(uint32_t a) { uint4 v; asm volatile("ld.shared.v4.b32 {%0,%1,%2,%3}, [%4];" : "=r"(v.x), "=r"(v.y), "=r"(v.z), "=r"(v.w) : "r"(a) : "memory"); return v; }
__device__ __forceinline__ float lds_bf(uint32_t a) { uint32_t v; asm volatile("ld.shared.u16 %0, [%1];" : "=r"(v) : "r"(a) : "memory"); return __uint_as_float(v << 16); }
__device__ __forceinline__ void sts(uint32_t a, uint32_t v) { asm volatile("st.shared.b32 [%0], %1;" ::"r"(a), "r"(v) : "memory"); }
__device__ __forceinline__ void sts2(uint32_t a, uint32_t v0, uint32_t v1) { asm volatile("st.shared.v2.b32 [%0], {%1,%2};" ::"r"(a), "r"(v0), "r"(v1) : "memory"); }
__device__ __forceinline__ void sts4(uint32_t a, uint32_t v0, uint32_t v1, uint32_t v2, uint32_t v3) { asm volatile("st.shared.v4.b32 [%0], {%1,%2,%3,%4};" ::"r"(a), "r"(v0), "r"(v1), "r"(v2), "r"(v3) : "memory"); }
__device__ __forceinline__ void bar_sync(int id, int n) { asm volatile("bar.sync %0, %1;" ::"r"(id), "r"(n) : "memory"); }
__device__ __forceinline__ void bar_arrive(int id, int n) { asm volatile("bar.arrive %0, %1;" ::"r"(id), "r"(n) : "memory"); }
__device__ __forceinline__ void red_add(unsigned* p, unsigned v) { asm volatile("red.relaxed.gpu.global.add.u32 [%0], %1;" ::"l"(p), "r"(v) : "memory"); }
__device__ __forceinline__ bool any(bool p) { return __any_sync(0xffffffffu, p); }
constexpr int SPIN_MAX = 1 << 20;
__device__ __forceinline__ void wait_cnt(const unsigned* p, unsigned target) {
  int it = 0;
  while (any((int)(ld_rlx(p) - target) < 0) && ++it < SPIN_MAX) {}
}
__device__ __forceinline__ uint32_t pack_bf16(float lo, float hi) { uint32_t r; asm("cvt.rn.bf16x2.f32 %0, %1, %2;" : "=r"(r) : "f"(hi), "f"(lo)); return r; }
__device__ __forceinline__ float bf_lo(uint32_t v) { return __uint_as_float(v << 16); }
__device__ __forceinline__ float bf_hi(uint32_t v) { return __uint_as_float(v & 0xffff0000u); }
__device__ __forceinline__ uint32_t hadd2(uint32_t a, uint32_t b) { uint32_t r; asm("add.rn.bf16x2 %0, %1, %2;" : "=r"(r) : "r"(a), "r"(b)); return r; }
__device__ __forceinline__ uint32_t hmul2(uint32_t a, uint32_t b) { uint32_t r; asm("mul.rn.bf16x2 %0, %1, %2;" : "=r"(r) : "r"(a), "r"(b)); return r; }
__device__ __forceinline__ uint32_t hfma2(uint32_t a, uint32_t b, uint32_t c) { uint32_t r; asm("fma.rn.bf16x2 %0, %1, %2, %3;" : "=r"(r) : "r"(a), "r"(b), "r"(c)); return r; }
__device__ __forceinline__ float rbf(float x) { uint32_t r; asm("cvt.rn.bf16x2.f32 %0, %1, %2;" : "=r"(r) : "f"(x), "f"(0.0f)); return __uint_as_float(r); }
__device__ __forceinline__ void stmatrix4(uint32_t a, uint32_t r0, uint32_t r1, uint32_t r2, uint32_t r3) {
  asm volatile("stmatrix.sync.aligned.m8n8.x4.shared.b16 [%0], {%1,%2,%3,%4};" ::"r"(a), "r"(r0), "r"(r1), "r"(r2), "r"(r3) : "memory");
}
__device__ __forceinline__ void stmatrix2(uint32_t a, uint32_t r0, uint32_t r1) {
  asm volatile("stmatrix.sync.aligned.m8n8.x2.shared.b16 [%0], {%1,%2};" ::"r"(a), "r"(r0), "r"(r1) : "memory");
}
__device__ __forceinline__ void stmatrix4t(uint32_t a, uint32_t r0, uint32_t r1, uint32_t r2, uint32_t r3) {
  asm volatile("stmatrix.sync.aligned.m8n8.x4.trans.shared.b16 [%0], {%1,%2,%3,%4};" ::"r"(a), "r"(r0), "r"(r1), "r"(r2), "r"(r3) : "memory");
}
__device__ __forceinline__ uint32_t movm(uint32_t a) { uint32_t r; asm("movmatrix.sync.aligned.m8n8.trans.b16 %0, %1;" : "=r"(r) : "r"(a)); return r; }
template <bool ACC> __device__ __forceinline__ void mma16(float* d, uint32_t a0, uint32_t a1, uint32_t a2, uint32_t a3, uint32_t b0, uint32_t b1) {
  if (ACC) asm("mma.sync.aligned.m16n8k16.row.col.f32.bf16.bf16.f32 {%0,%1,%2,%3}, {%4,%5,%6,%7}, {%8,%9}, {%0,%1,%2,%3};"
               : "+f"(d[0]), "+f"(d[1]), "+f"(d[2]), "+f"(d[3]) : "r"(a0), "r"(a1), "r"(a2), "r"(a3), "r"(b0), "r"(b1));
  else asm("mma.sync.aligned.m16n8k16.row.col.f32.bf16.bf16.f32 {%0,%1,%2,%3}, {%4,%5,%6,%7}, {%8,%9}, {%10,%10,%10,%10};"
           : "=f"(d[0]), "=f"(d[1]), "=f"(d[2]), "=f"(d[3]) : "r"(a0), "r"(a1), "r"(a2), "r"(a3), "r"(b0), "r"(b1), "f"(0.f));
}
__device__ __forceinline__ uint32_t pin(uint32_t v) { uint32_t r; asm volatile("shfl.sync.bfly.b32 %0, %1, 0, 31, 0xffffffff;" : "=r"(r) : "r"(v)); return r; }
__device__ __forceinline__ uint32_t set_tag(uint32_t w, uint32_t tag) { uint32_t r; asm("lop3.b32 %0, %1, 0xfffffffe, %2, 0xea;" : "=r"(r) : "r"(w), "r"(tag)); return r; }
__device__ __forceinline__ uint32_t diff2(uint32_t a, uint32_t b, uint32_t tag) { uint32_t r; asm("lop3.b32 %0, %1, %2, %3, 0x7e;" : "=r"(r) : "r"(a), "r"(b), "r"(tag)); return r; }
__device__ __forceinline__ float2 cmul(float2 a, float2 b) { return make_float2(a.x * b.x - a.y * b.y, a.x * b.y + a.y * b.x); }

template<int TB> __device__ __forceinline__ void wgmma_ss_160_0(float (&d)[80], uint32_t al, uint32_t ah, uint32_t bl, uint32_t bh) {
  asm volatile("{\n.reg .b64 da, db;\nmov.b64 da, {%80, %81};\nmov.b64 db, {%82, %83};\n"
    "wgmma.mma_async.sync.aligned.m64n160k16.f32.bf16.bf16 {%0,%1,%2,%3,%4,%5,%6,%7,%8,%9,%10,%11,%12,%13,%14,%15,%16,%17,%18,%19,%20,%21,%22,%23,%24,%25,%26,%27,%28,%29,%30,%31,%32,%33,%34,%35,%36,%37,%38,%39,%40,%41,%42,%43,%44,%45,%46,%47,%48,%49,%50,%51,%52,%53,%54,%55,%56,%57,%58,%59,%60,%61,%62,%63,%64,%65,%66,%67,%68,%69,%70,%71,%72,%73,%74,%75,%76,%77,%78,%79}, da, db, 1, 1, 1, 1, %84;\n}\n"
    : "+f"(d[0]),"+f"(d[1]),"+f"(d[2]),"+f"(d[3]),"+f"(d[4]),"+f"(d[5]),"+f"(d[6]),"+f"(d[7]),"+f"(d[8]),"+f"(d[9]),"+f"(d[10]),"+f"(d[11]),"+f"(d[12]),"+f"(d[13]),"+f"(d[14]),"+f"(d[15]),"+f"(d[16]),"+f"(d[17]),"+f"(d[18]),"+f"(d[19]),"+f"(d[20]),"+f"(d[21]),"+f"(d[22]),"+f"(d[23]),"+f"(d[24]),"+f"(d[25]),"+f"(d[26]),"+f"(d[27]),"+f"(d[28]),"+f"(d[29]),"+f"(d[30]),"+f"(d[31]),"+f"(d[32]),"+f"(d[33]),"+f"(d[34]),"+f"(d[35]),"+f"(d[36]),"+f"(d[37]),"+f"(d[38]),"+f"(d[39]),"+f"(d[40]),"+f"(d[41]),"+f"(d[42]),"+f"(d[43]),"+f"(d[44]),"+f"(d[45]),"+f"(d[46]),"+f"(d[47]),"+f"(d[48]),"+f"(d[49]),"+f"(d[50]),"+f"(d[51]),"+f"(d[52]),"+f"(d[53]),"+f"(d[54]),"+f"(d[55]),"+f"(d[56]),"+f"(d[57]),"+f"(d[58]),"+f"(d[59]),"+f"(d[60]),"+f"(d[61]),"+f"(d[62]),"+f"(d[63]),"+f"(d[64]),"+f"(d[65]),"+f"(d[66]),"+f"(d[67]),"+f"(d[68]),"+f"(d[69]),"+f"(d[70]),"+f"(d[71]),"+f"(d[72]),"+f"(d[73]),"+f"(d[74]),"+f"(d[75]),"+f"(d[76]),"+f"(d[77]),"+f"(d[78]),"+f"(d[79])
    : "r"(al), "r"(ah), "r"(bl), "r"(bh), "n"(TB));
}
template<int TB> __device__ __forceinline__ void wgmma_ss_144_0(float (&d)[80], uint32_t al, uint32_t ah, uint32_t bl, uint32_t bh) {
  asm volatile("{\n.reg .b64 da, db;\nmov.b64 da, {%72, %73};\nmov.b64 db, {%74, %75};\n"
    "wgmma.mma_async.sync.aligned.m64n144k16.f32.bf16.bf16 {%0,%1,%2,%3,%4,%5,%6,%7,%8,%9,%10,%11,%12,%13,%14,%15,%16,%17,%18,%19,%20,%21,%22,%23,%24,%25,%26,%27,%28,%29,%30,%31,%32,%33,%34,%35,%36,%37,%38,%39,%40,%41,%42,%43,%44,%45,%46,%47,%48,%49,%50,%51,%52,%53,%54,%55,%56,%57,%58,%59,%60,%61,%62,%63,%64,%65,%66,%67,%68,%69,%70,%71}, da, db, 1, 1, 1, 1, %76;\n}\n"
    : "+f"(d[0]),"+f"(d[1]),"+f"(d[2]),"+f"(d[3]),"+f"(d[4]),"+f"(d[5]),"+f"(d[6]),"+f"(d[7]),"+f"(d[8]),"+f"(d[9]),"+f"(d[10]),"+f"(d[11]),"+f"(d[12]),"+f"(d[13]),"+f"(d[14]),"+f"(d[15]),"+f"(d[16]),"+f"(d[17]),"+f"(d[18]),"+f"(d[19]),"+f"(d[20]),"+f"(d[21]),"+f"(d[22]),"+f"(d[23]),"+f"(d[24]),"+f"(d[25]),"+f"(d[26]),"+f"(d[27]),"+f"(d[28]),"+f"(d[29]),"+f"(d[30]),"+f"(d[31]),"+f"(d[32]),"+f"(d[33]),"+f"(d[34]),"+f"(d[35]),"+f"(d[36]),"+f"(d[37]),"+f"(d[38]),"+f"(d[39]),"+f"(d[40]),"+f"(d[41]),"+f"(d[42]),"+f"(d[43]),"+f"(d[44]),"+f"(d[45]),"+f"(d[46]),"+f"(d[47]),"+f"(d[48]),"+f"(d[49]),"+f"(d[50]),"+f"(d[51]),"+f"(d[52]),"+f"(d[53]),"+f"(d[54]),"+f"(d[55]),"+f"(d[56]),"+f"(d[57]),"+f"(d[58]),"+f"(d[59]),"+f"(d[60]),"+f"(d[61]),"+f"(d[62]),"+f"(d[63]),"+f"(d[64]),"+f"(d[65]),"+f"(d[66]),"+f"(d[67]),"+f"(d[68]),"+f"(d[69]),"+f"(d[70]),"+f"(d[71])
    : "r"(al), "r"(ah), "r"(bl), "r"(bh), "n"(TB));
}
template<int TB> __device__ __forceinline__ void wgmma_ss_96_0(float (&d)[80], uint32_t al, uint32_t ah, uint32_t bl, uint32_t bh) {
  asm volatile("{\n.reg .b64 da, db;\nmov.b64 da, {%48, %49};\nmov.b64 db, {%50, %51};\n"
    "wgmma.mma_async.sync.aligned.m64n96k16.f32.bf16.bf16 {%0,%1,%2,%3,%4,%5,%6,%7,%8,%9,%10,%11,%12,%13,%14,%15,%16,%17,%18,%19,%20,%21,%22,%23,%24,%25,%26,%27,%28,%29,%30,%31,%32,%33,%34,%35,%36,%37,%38,%39,%40,%41,%42,%43,%44,%45,%46,%47}, da, db, 1, 1, 1, 1, %52;\n}\n"
    : "+f"(d[0]),"+f"(d[1]),"+f"(d[2]),"+f"(d[3]),"+f"(d[4]),"+f"(d[5]),"+f"(d[6]),"+f"(d[7]),"+f"(d[8]),"+f"(d[9]),"+f"(d[10]),"+f"(d[11]),"+f"(d[12]),"+f"(d[13]),"+f"(d[14]),"+f"(d[15]),"+f"(d[16]),"+f"(d[17]),"+f"(d[18]),"+f"(d[19]),"+f"(d[20]),"+f"(d[21]),"+f"(d[22]),"+f"(d[23]),"+f"(d[24]),"+f"(d[25]),"+f"(d[26]),"+f"(d[27]),"+f"(d[28]),"+f"(d[29]),"+f"(d[30]),"+f"(d[31]),"+f"(d[32]),"+f"(d[33]),"+f"(d[34]),"+f"(d[35]),"+f"(d[36]),"+f"(d[37]),"+f"(d[38]),"+f"(d[39]),"+f"(d[40]),"+f"(d[41]),"+f"(d[42]),"+f"(d[43]),"+f"(d[44]),"+f"(d[45]),"+f"(d[46]),"+f"(d[47])
    : "r"(al), "r"(ah), "r"(bl), "r"(bh), "n"(TB));
}
template<int TB> __device__ __forceinline__ void wgmma_ss_48_48(float (&d)[80], uint32_t al, uint32_t ah, uint32_t bl, uint32_t bh) {
  asm volatile("{\n.reg .b64 da, db;\nmov.b64 da, {%24, %25};\nmov.b64 db, {%26, %27};\n"
    "wgmma.mma_async.sync.aligned.m64n48k16.f32.bf16.bf16 {%0,%1,%2,%3,%4,%5,%6,%7,%8,%9,%10,%11,%12,%13,%14,%15,%16,%17,%18,%19,%20,%21,%22,%23}, da, db, 1, 1, 1, 1, %28;\n}\n"
    : "+f"(d[48]),"+f"(d[49]),"+f"(d[50]),"+f"(d[51]),"+f"(d[52]),"+f"(d[53]),"+f"(d[54]),"+f"(d[55]),"+f"(d[56]),"+f"(d[57]),"+f"(d[58]),"+f"(d[59]),"+f"(d[60]),"+f"(d[61]),"+f"(d[62]),"+f"(d[63]),"+f"(d[64]),"+f"(d[65]),"+f"(d[66]),"+f"(d[67]),"+f"(d[68]),"+f"(d[69]),"+f"(d[70]),"+f"(d[71])
    : "r"(al), "r"(ah), "r"(bl), "r"(bh), "n"(TB));
}
__device__ __forceinline__ void wgmma_rs_72(float (&d)[36], uint32_t a0, uint32_t a1, uint32_t a2, uint32_t a3, uint32_t bl, uint32_t bh, int sd) {
  asm volatile("{\n.reg .pred p;\n.reg .b64 db;\nsetp.ne.b32 p, %42, 0;\nmov.b64 db, {%40, %41};\n"
    "wgmma.mma_async.sync.aligned.m64n72k16.f32.bf16.bf16 {%0,%1,%2,%3,%4,%5,%6,%7,%8,%9,%10,%11,%12,%13,%14,%15,%16,%17,%18,%19,%20,%21,%22,%23,%24,%25,%26,%27,%28,%29,%30,%31,%32,%33,%34,%35}, {%36,%37,%38,%39}, db, p, 1, 1, 1;\n}\n"
    : "+f"(d[0]),"+f"(d[1]),"+f"(d[2]),"+f"(d[3]),"+f"(d[4]),"+f"(d[5]),"+f"(d[6]),"+f"(d[7]),"+f"(d[8]),"+f"(d[9]),"+f"(d[10]),"+f"(d[11]),"+f"(d[12]),"+f"(d[13]),"+f"(d[14]),"+f"(d[15]),"+f"(d[16]),"+f"(d[17]),"+f"(d[18]),"+f"(d[19]),"+f"(d[20]),"+f"(d[21]),"+f"(d[22]),"+f"(d[23]),"+f"(d[24]),"+f"(d[25]),"+f"(d[26]),"+f"(d[27]),"+f"(d[28]),"+f"(d[29]),"+f"(d[30]),"+f"(d[31]),"+f"(d[32]),"+f"(d[33]),"+f"(d[34]),"+f"(d[35])
    : "r"(a0), "r"(a1), "r"(a2), "r"(a3), "r"(bl), "r"(bh), "r"(sd));
}
__device__ __forceinline__ void wgmma_rs_48(float (&d)[24], uint32_t a0, uint32_t a1, uint32_t a2, uint32_t a3, uint32_t bl, uint32_t bh, int sd) {
  asm volatile("{\n.reg .pred p;\n.reg .b64 db;\nsetp.ne.b32 p, %30, 0;\nmov.b64 db, {%28, %29};\n"
    "wgmma.mma_async.sync.aligned.m64n48k16.f32.bf16.bf16 {%0,%1,%2,%3,%4,%5,%6,%7,%8,%9,%10,%11,%12,%13,%14,%15,%16,%17,%18,%19,%20,%21,%22,%23}, {%24,%25,%26,%27}, db, p, 1, 1, 1;\n}\n"
    : "+f"(d[0]),"+f"(d[1]),"+f"(d[2]),"+f"(d[3]),"+f"(d[4]),"+f"(d[5]),"+f"(d[6]),"+f"(d[7]),"+f"(d[8]),"+f"(d[9]),"+f"(d[10]),"+f"(d[11]),"+f"(d[12]),"+f"(d[13]),"+f"(d[14]),"+f"(d[15]),"+f"(d[16]),"+f"(d[17]),"+f"(d[18]),"+f"(d[19]),"+f"(d[20]),"+f"(d[21]),"+f"(d[22]),"+f"(d[23])
    : "r"(a0), "r"(a1), "r"(a2), "r"(a3), "r"(bl), "r"(bh), "r"(sd));
}
template<int N,int OFF,int TB> __device__ __forceinline__ void wgmma_ss(float (&d)[80], uint32_t al, uint32_t ah, uint32_t bl, uint32_t bh) {
  if constexpr (N==160) wgmma_ss_160_0<TB>(d, al, ah, bl, bh);
  else if constexpr (N==144) wgmma_ss_144_0<TB>(d, al, ah, bl, bh);
  else if constexpr (N==96) wgmma_ss_96_0<TB>(d, al, ah, bl, bh);
  else if constexpr (N==48) wgmma_ss_48_48<TB>(d, al, ah, bl, bh);
}

__device__ __forceinline__ void dft3(float2& a, float2& b, float2& c) {
  const float s = 0.86602540378443864676f;
  float2 t = make_float2(b.x + c.x, b.y + c.y), d = make_float2(b.x - c.x, b.y - c.y);
  float2 m = make_float2(fmaf(-0.5f, t.x, a.x), fmaf(-0.5f, t.y, a.y));
  a = make_float2(a.x + t.x, a.y + t.y);
  b = make_float2(fmaf(s, d.y, m.x), fmaf(-s, d.x, m.y));
  c = make_float2(fmaf(-s, d.y, m.x), fmaf(s, d.x, m.y));
}
__device__ __forceinline__ void dft9(float2 (&x)[9]) {
  const float2 w1 = make_float2(0.76604444311897803520f, -0.64278760968653932632f);
  const float2 w2 = make_float2(0.17364817766693034885f, -0.98480775301220805937f);
  const float2 w4 = make_float2(-0.93969262078590838405f, -0.34202014332566873304f);
  dft3(x[0], x[3], x[6]); dft3(x[1], x[4], x[7]); dft3(x[2], x[5], x[8]);
  x[4] = cmul(x[4], w1); x[7] = cmul(x[7], w2); x[5] = cmul(x[5], w2); x[8] = cmul(x[8], w4);
  dft3(x[0], x[1], x[2]); dft3(x[3], x[4], x[5]); dft3(x[6], x[7], x[8]);
  float2 t;
  t = x[1]; x[1] = x[3]; x[3] = t;
  t = x[2]; x[2] = x[6]; x[6] = t;
  t = x[5]; x[5] = x[7]; x[7] = t;
}

__device__ __forceinline__ int mod_pos(int u, int i) { return 16 * u + (u < 72 ? 2 * (i & 7) + (i >> 3) : i); }
__device__ __forceinline__ void mod_fma(float (&acc)[8], float sc, const uint4& w) {
  acc[0] = fmaf(sc, bf_lo(w.x), acc[0]); acc[1] = fmaf(sc, bf_hi(w.x), acc[1]);
  acc[2] = fmaf(sc, bf_lo(w.y), acc[2]); acc[3] = fmaf(sc, bf_hi(w.y), acc[3]);
  acc[4] = fmaf(sc, bf_lo(w.z), acc[4]); acc[5] = fmaf(sc, bf_hi(w.z), acc[5]);
  acc[6] = fmaf(sc, bf_lo(w.w), acc[6]); acc[7] = fmaf(sc, bf_hi(w.w), acc[7]);
}
__device__ __forceinline__ void mod_finish(const Params& p, float (&acc)[8], int u, int t128, uint32_t rb, uint32_t tag) {
#pragma unroll
  for (int n = 4, o = 2; n; n >>= 1, o <<= 1) {
    const bool up = t128 & o;
#pragma unroll
    for (int e = 0; e < n; e++) acc[e] = (up ? acc[e + n] : acc[e]) + __shfl_xor_sync(0xffffffffu, up ? acc[e] : acc[e + n], o);
  }
  acc[0] += __shfl_xor_sync(0xffffffffu, acc[0], 16);
  const int col = 8 * (t128 & 1) + 2 * (t128 & 2) + ((t128 >> 1) & 2) + ((t128 >> 3) & 1);
  if (!(t128 & 16)) sts(rb + (col * 4 + (t128 >> 5)) * 4, __float_as_uint(acc[0]));
  bar_sync(4, 128);
  if (t128 < 16) {
    const uint4 v = lds4(rb + t128 * 16);
    float m = rbf((__uint_as_float(v.x) + __uint_as_float(v.y)) + (__uint_as_float(v.z) + __uint_as_float(v.w)));
    const int kind = u / 36;
    if (kind == 0) m *= 16.0f;
    if (kind == 1 || kind == 4) m = rbf(1.0f + m);
    p.s->mod[mod_pos(u, t128)] = __float_as_uint(m) | tag;
  }
}

__device__ __forceinline__ void ln_stats2(const float (&a)[18], const float (&b)[18], float sc, float& oa, float& ra, float& ob, float& rb) {
  float v[4] = {0.f, 0.f, 0.f, 0.f}, w[4] = {0.f, 0.f, 0.f, 0.f};
#pragma unroll
  for (int i = 0; i < 18; i += 2) {
    v[0] += a[i]; v[1] = fmaf(a[i], a[i], v[1]); v[2] += b[i]; v[3] = fmaf(b[i], b[i], v[3]);
    w[0] += a[i + 1]; w[1] = fmaf(a[i + 1], a[i + 1], w[1]); w[2] += b[i + 1]; w[3] = fmaf(b[i + 1], b[i + 1], w[3]);
  }
#pragma unroll
  for (int e = 0; e < 4; e++) v[e] += w[e];
#pragma unroll
  for (int o = 16; o; o >>= 1) {
#pragma unroll
    for (int e = 0; e < 4; e++) v[e] += __shfl_xor_sync(0xffffffffu, v[e], o);
  }
  const float ma = v[0] * (1.0f / D_), mb = v[2] * (1.0f / D_);
  ra = sc * rsqrtf(fmaxf(fmaf(-ma, ma, v[1] * (1.0f / D_)), 0.f) + 1e-5f);
  rb = sc * rsqrtf(fmaxf(fmaf(-mb, mb, v[3] * (1.0f / D_)), 0.f) + 1e-5f);
  oa = -ma * ra; ob = -mb * rb;
}

__device__ __forceinline__ float tmat(int c, int q, int j) {
  const int ph = q == 1 ? 1024 * j : (q >> 1) * (c + 128 * j) + 512 * (q & 1);
  return __cosf((float)(((ph + 1024) & 2047) - 1024) * (6.283185307179586f / 2048.0f));
}
__device__ __forceinline__ uint32_t line_off(int k1, int kap, int pi, int f) {
  int kd = 64 * k1 + 9 * kap;
  if (kap == 0 && k1 > 4) kd -= 288;
  if (kd >= D_) kd -= D_;
  return pi * 2400 + ((min(kd, D_ - kd) ^ f) << 3);
}

constexpr int JSK = 5;
struct Ring { uint32_t st, ph; };
template <bool G2, class T> __device__ __forceinline__ void ring_next(T& st, T& ph) {
  if (++st == NST) st = 0;
  ph ^= ((G2 ? 0xDu : 0x1u) >> st) & 1;
}
__device__ __forceinline__ void arrive_if(uint32_t a, uint32_t p) {
  asm volatile("{\n.reg .pred p;\nsetp.ne.u32 p, %1, 0;\n@p mbarrier.arrive.shared::cta.b64 _, [%0];\n}" ::"r"(a), "r"(p) : "memory");
}
template <int NA> __device__ __forceinline__ void reg_fence_n(float (&d)[80]) {
#pragma unroll
  for (int i = 0; i < NA; i++) asm volatile("" : "+f"(d[i])::"memory");
}
template <int MODE>
__device__ __forceinline__ void gemm_main(float (&acc)[80], uint32_t da0, uint32_t da1, uint32_t db0, uint32_t db1, int wg, Ring& rg,
                                          uint32_t* x1p, const uint32_t (&xr)[18]) {
  static_assert(JSK == NST - 1, "the held slot is the first one that is not refilled by GEMM1");
  constexpr int NKB = MODE == 3 ? 36 : 32;
  constexpr uint32_t HA = 0x40000040u, HB = MODE == 3 ? 0x40000040u : 0x80000020u;
  constexpr uint32_t KA = 2048 >> 4, KB = MODE == 3 ? (32 >> 4) : (1024 >> 4);
  constexpr int NA = MODE ? 72 : 80;
  const uint32_t t = threadIdx.x & 127;
  const uint32_t eb = full0 + 8 * NST;
  uint32_t pb = 0, rel = t == 0, prel = 0, ok = 0;
  int n = MODE == 3 ? NKB - JSK : X1K + 2 * wg;
#pragma unroll 1
  for (int pass = MODE == 3 ? 0 : -1;; pass++) {
#pragma unroll 1
    do {
      const uint32_t so = rg.st * (STAGE >> 4), cb = eb + 8 * rg.st;
      if (__builtin_expect(!ok, 0)) mbar_wait(full0 + 8 * rg.st, rg.ph);
      reg_fence_n<NA>(acc);
      wg_fence();
#pragma unroll
      for (int k = 0; k < 4; k++) {
        if (k == 3) { ring_next<MODE == 3>(rg.st, rg.ph); ok = PEEK ? mbar_test(full0 + 8 * rg.st, rg.ph) : 0; }
        if (MODE == 0) wgmma_ss<160, 0, 1>(acc, da0 + so + k * KA, HA, db0 + so + k * KB, HB);
        else if (MODE == 3) wgmma_ss<144, 0, 0>(acc, da0 + so + k * KA, HA, db0 + so + k * KB, HB);
        else {
          wgmma_ss<96, 0, 1>(acc, da0 + so + k * KA, HA, db0 + so + k * KB, HB);
          wgmma_ss<48, 48, 1>(acc, da1 + so + k * KA, HA, db1 + so + k * KB, HB);
        }
      }
      wg_commit();
      wg_wait<1>();
      reg_fence_n<NA>(acc);
      arrive_if(pb, prel);
      pb = cb; prel = rel;
    } while (--n);
    if (pass == 2 - wg) break;
    if (MODE != 3 && pass < 0) {
      if (blockIdx.x < 128) {
#pragma unroll
        for (int i = 0; i < 9; i++) { x1p[32 * i] = xr[i]; x1p[128 * 288 + 32 * i] = xr[9 + i]; }
      }
      n = NKB - JSK - X1K - 2 * wg;
      continue;
    }
    n = 1;
    if (pass == 0) {
      if (MODE != 3) prel = rel & wg;
      else rel = 0;
      n = JSK - 1 + wg;
      if (!wg) continue;
      wg_wait<0>();
      arrive_if(pb, prel);
      prel = 0;
    }
    bar_sync(1, 256);
  }
  wg_wait<0>();
  reg_fence_n<NA>(acc);
  if (MODE != 3) arrive_if(pb, prel & ~wg);
}

__device__ __forceinline__ float gelu_arg(float h) { return h * fmaf(8.0f * 0.044715f * 0.7978845608028654f, h * h, 2.0f * 0.7978845608028654f); }

__device__ __forceinline__ int kb2_order(int i) { const int wv = i / 6; return 6 * (i - 6 * wv) + ((0x431250 >> (4 * wv)) & 7); }

__device__ __forceinline__ void wait_flags(const unsigned* base, int n, int idx, unsigned target, uint64_t& ready) {
  if ((ready >> idx) & 1) return;
  const int l = threadIdx.x & 31;
  int it = 0;
  while (true) {
    unsigned a = ld_rlx(base + l), b = l + 32 < n ? ld_rlx(base + l + 32) : target;
    ready = (uint64_t)__ballot_sync(0xffffffffu, (int)(a - target) >= 0) | ((uint64_t)__ballot_sync(0xffffffffu, (int)(b - target) >= 0) << 32);
    if (((ready >> idx) & 1) || ++it > SPIN_MAX) break;
  }
  fence_async_glb();
}

enum { B_FULL = 0, B_EMPTY = 6, B_FLT = 12, B_Z1, B_Z2, B_GO, B_S4, B_S5, B_WM, B_NUM, B_W0 = B_NUM };

__global__ void __launch_bounds__(NTHR, 1)
fused_kernel(const Params p, const __grid_constant__ Maps maps) {
  extern __shared__ __align__(1024) uint8_t smem_raw[];
  const int tid = threadIdx.x, cta = blockIdx.x, t128 = tid & 127;
  const int wp = __shfl_sync(0xffffffffu, tid >> 5, 0), wg = wp >> 2;
  const int l = tid & 31, g = l >> 2, t = l & 3;
  Scratch* const sc = p.s;
  const bool rows = cta < 128;
  const int R = cta - 12;

  uint32_t xr[18];
  uint32_t cv[9];
  const unsigned ep = ld_rlx(&sc->cnt[C_EP]) + 1;
  if (tid == 0) TS(0);
  if (wg == 2) {
#pragma unroll
    for (int i = 0; i < 9; i++) asm volatile("ld.global.nc.u16 %0, [%1];" : "=r"(cv[i]) : "l"(p.c + (t128 >> 1) + 64 * i) : "memory");
    if (wp == 9 && l < 9 && rows) {
      const int h = 9 * cta + l;
      prefetch_l2(reinterpret_cast<const uint8_t*>(p.wmod) + (size_t)(h >> 1) * (12 * D_) + (h & 1) * (2 * D_), 2 * D_);
    }
    if (t128 < 16) {
#pragma unroll 1
      for (int u = cta < 72 ? cta : 72 + cta; u < 216; u += u < 72 ? 72 : NCTA) sc->mod[mod_pos(u, t128)] = 0;
    }
    if (tid == 256 && cta < 72) {
      mbar_init(full0 + 8 * B_W0, 1);
      fence_async_smem();
      mbar_expect(full0 + 8 * B_W0, 18432);
#pragma unroll 1
      for (int i = 0; i < 3; i++) tma2d(sbase + O_P2 + i * 6144, &maps.wm, 16 * cta, 192 * i, full0 + 8 * B_W0);
    }
    if (wp == 11 && smem_u32(smem_raw) != sbase) __trap();
    if (tid == 352) {
#pragma unroll 1
      for (int i = 0; i < B_NUM; i++) mbar_init(full0 + 8 * i, i == B_FLT ? 4 : i == B_WM ? 3 : (i >= B_EMPTY && i < B_FLT) || i == B_S4 || i == B_S5 ? 2 : 1);
      fence_async_smem();
    }
    if (wp == 10 && l < 12) asm volatile("prefetch.tensormap [%0];" ::"l"(&maps.w1a + l) : "memory");
    __syncwarp();
  }
  CK(0);
  auto load_x = [&]() {
    const uint32_t* xs = reinterpret_cast<const uint32_t*>(p.x) + (size_t)(cta + 256 * wp) * 288 + l;
#pragma unroll
    for (int i = 0; i < 9; i++) { xr[i] = ld_nc(xs + 32 * i); xr[9 + i] = ld_nc(xs + 128 * 288 + 32 * i); }
  };
  if (rows && wg < 2) load_x();
  if (tid == 64 && cta == NCTA - 1) prefetch_l2(p.tab, sizeof(T_TAB));
  __syncwarp();
  const uint32_t tag16 = (ep & 0x7fffu) | 0x8000u, tag1 = ep & 1u;

  if (wg == 2) {
    float sil[9];
#pragma unroll
    for (int i = 0; i < 9; i++) sil[i] = rbf(__fdividef(bf_lo(cv[i]), 1.0f + __expf(-bf_lo(cv[i]))));
    if (cta < 72) {
      float acc[8] = {0.f, 0.f, 0.f, 0.f, 0.f, 0.f, 0.f, 0.f};
      bar_sync(4, 128);
      mbar_wait(full0 + 8 * B_W0, 0);
      if (t128 == 0) TS(10);
#pragma unroll
      for (int i = 0; i < 9; i++) mod_fma(acc, sil[i], lds4(sbase + O_P2 + t128 * 16 + i * 2048));
      mod_finish(p, acc, cta, t128, red, tag16);
      if (t128 == 0) TS(25);
    }
#pragma unroll
    for (int i = 0; i < 9; i++) sts(red + 512 + ((t128 >> 1) + 64 * i) * 4, __float_as_uint(sil[i]));
    CK(1);
  }
  const int pi = R / 15, col0 = 20 * (R - 15 * pi);
  const int xu = DF_ * pi + col0, xv = DF_ * (pi ? 16 - pi : 8) + col0;
  auto load_filter = [&](int a) {
    const int x = (a & 1) ? xv : xu;
    const bool wide = (x & 15) > 12;
    mbar_expect(full0 + 8 * B_FLT, wide ? 12288 : 8192);
    tma2d(sbase + O_RAW + a * 12288, &maps.wf[a & 2], x & ~15, 0, full0 + 8 * B_FLT);
    if (wide) tma2d(sbase + O_RAW + a * 12288 + 8192, &maps.wf[(a & 2) + 1], (x & ~15) + 32, 0, full0 + 8 * B_FLT);
  };
  const int kap = 8 * ((wp & 3) ^ (wg & 1)) + g;
  uint4 af[4];
  if (rows) {
    uint32_t tb[4];
#pragma unroll
    for (int i = 0; i < 4; i++) tb[i] = pack_bf16(tmat(cta, 8 * (i >> 1) + g, 2 * t + 8 * (i & 1)), tmat(cta, 8 * (i >> 1) + g, 2 * t + 8 * (i & 1) + 1));
    uint32_t sb1[3], lo[9];
#pragma unroll
    for (int i = 0; i < 4; i++) tb[i] = pin(tb[i]);
#pragma unroll
    for (int i = 0; i < 3; i++) {
      const int d = 48 * wp + 16 * i + (l & 15);
      sb1[i] = pin(sbase + O_B1 + (l >> 4) * 9216 + (d % 9) * 1024 + (d & 63) * 16);
    }
    const uint32_t snt = pin(sbase + O_NRM + ((l & 7) + 8 * (l >> 4)) * 1168 + (48 * wp + (l & 8)) * 2);
    if (wg < 2) {
#pragma unroll
      for (int k1 = 0; k1 < 9; k1++) lo[k1] = pin(sbase + O_Z1 + line_off(k1, kap, 4 * wg + t, cta & 3));
#pragma unroll
      for (int kk = 0; kk < 4; kk++) af[kk] = __ldg(p.tab + TB_F + kk * 128 + (t128 ^ (wg << 5)));
      float a[18], b[18];
#pragma unroll
      for (int i = 0; i < 9; i++) { a[2 * i] = bf_lo(xr[i]); a[2 * i + 1] = bf_hi(xr[i]); b[2 * i] = bf_lo(xr[9 + i]); b[2 * i + 1] = bf_hi(xr[9 + i]); }
      float oa, ra, ob, rb;
      ln_stats2(a, b, 1.0f, oa, ra, ob, rb);
      CK(1);
      const uint32_t sn = sbase + O_NRM + wp * 2336 + l * 4;
#pragma unroll
      for (int i = 0; i < 9; i++) {
        sts(sn + i * 128, pack_bf16(fmaf(a[2 * i], ra, oa), fmaf(a[2 * i + 1], ra, oa)));
        sts(sn + 1168 + i * 128, pack_bf16(fmaf(b[2 * i], rb, ob), fmaf(b[2 * i + 1], rb, ob)));
      }
      CK(2);
      bar_arrive(10, NTHR);
      bar_sync(1, 256);
      if (tid == 0) TS(2);
    } else {
      bar_sync(10, NTHR);
      CK(2);
    }
    float rs[3][8];
#pragma unroll
    for (int i = 0; i < 3; i++) {
      uint32_t a0, a1, a2, a3;
      asm volatile("ldmatrix.sync.aligned.m8n8.x4.trans.shared.b16 {%0,%1,%2,%3}, [%4];" : "=r"(a0), "=r"(a1), "=r"(a2), "=r"(a3)
                   : "r"(snt + 32 * i) : "memory");
      mma16<false>(&rs[i][0], a0, a1, a2, a3, tb[0], tb[1]);
      mma16<false>(&rs[i][4], a0, a1, a2, a3, tb[2], tb[3]);
    }
    CK(3);
    {
      uint2 ms[3], mc[3];
      const uint32_t* mp = sc->mod + 48 * wp + 2 * g;
      int it = 0;
#pragma unroll 1
      while (true) {
        uint32_t bad = 0;
#pragma unroll
        for (int i = 0; i < 3; i++) { ms[i] = ld_rlx2(mp + 16 * i); mc[i] = ld_rlx2(mp + D_ + 16 * i); }
#pragma unroll
        for (int i = 0; i < 3; i++) {
          ms[i].x ^= tag16; ms[i].y ^= tag16; mc[i].x ^= tag16; mc[i].y ^= tag16;
          bad |= ms[i].x | ms[i].y | mc[i].x | mc[i].y;
        }
        if (!any(bad & 0xffffu) || ++it > SPIN_MAX) break;
      }
      CK(4);
      if (tid == 0) TS(3);
#pragma unroll
      for (int i = 0; i < 3; i++) {
        const float c0 = __uint_as_float(mc[i].x), c1 = __uint_as_float(mc[i].y);
        const float s0 = t ? 0.f : __uint_as_float(ms[i].x), s1 = t ? 0.f : __uint_as_float(ms[i].y);
        stmatrix4(sb1[i], pack_bf16(fmaf(rs[i][0], c0, s0), rs[i][1] * c0), pack_bf16(fmaf(rs[i][2], c1, s1), rs[i][3] * c1),
                  pack_bf16(rs[i][4] * c0, rs[i][5] * c0), pack_bf16(rs[i][6] * c1, rs[i][7] * c1));
      }
    }
    fence_async_smem();
    CK(5);
    if (wg == 2) {
      bar_arrive(5, NTHR);
      if (l == 0 && R >= 0) load_filter(wp - 8);
      __syncwarp();
    } else {
      bar_sync(5, NTHR);
      CK(6);
      float acc[36];
      const uint32_t db = (((sbase + O_B1 + wg * 9216) & 0x3FFFF) >> 4) | ((128 >> 4) << 16);
      wg_fence();
#pragma unroll
      for (int kk = 0; kk < 4; kk++) wgmma_rs_72(acc, af[kk].x, af[kk].y, af[kk].z, af[kk].w, db + kk * 16, 1024 >> 4, kk);
      wg_commit();
      wg_wait<0>();
      reg_fence(acc);
      CK(7);
      float2 za[9], zb[9];
#pragma unroll
      for (int i = 0; i < 9; i++) { za[i] = make_float2(acc[4 * i], acc[4 * i + 2]); zb[i] = make_float2(acc[4 * i + 1], acc[4 * i + 3]); }
      dft9(za); dft9(zb);
      if (kap == 0) {
#pragma unroll
        for (int k = 1; k < 5; k++) {
          float2 a = za[k], b = za[9 - k];
          za[k] = make_float2(a.x + b.x, a.y - b.y); za[9 - k] = make_float2(a.y + b.y, b.x - a.x);
          a = zb[k]; b = zb[9 - k];
          zb[k] = make_float2(a.x + b.x, a.y - b.y); zb[9 - k] = make_float2(a.y + b.y, b.x - a.x);
        }
        sts2(lo[0] + 288 * 8, set_tag(pack_bf16(za[0].y, 0.f), tag1), pack_bf16(zb[0].y, 0.f));
        za[0].y = 0.f; zb[0].y = 0.f;
      }
      __syncwarp();
#pragma unroll
      for (int k1 = 0; k1 < 9; k1++) sts2(lo[k1], set_tag(pack_bf16(za[k1].x, za[k1].y), tag1), pack_bf16(zb[k1].x, zb[k1].y));
      fence_async_smem();
      CK(8);
      bar_arrive(2 + wg, 160);
    }
  } else {
    __syncthreads();
  }

  if ((wp >> 1) == 4) {
    if (rows) bar_sync(wp - 6, 160);
    else { int it = 0; while (any((ld_rlx(sc->mod + 36 * l) ^ tag16) & 0xffffu) && ++it < SPIN_MAX) {} }
    if (l == 0) {
      const int slot = 4 * (cta & 7) + ((cta >> 4) & 3) + 32 * (2 * (cta >> 6) + ((cta >> 3) & 1));
      if (rows) {
        tma_st2d(&maps.z1, sbase + O_Z1 + (wp - 8) * 9600, 40 * slot, 60 * (wp - 8));
        HW();
        red_add(&sc->cnt[C_Z1 + 32 * (wp - 8)], 1);
        if (wp == 8) TS(4);
      } else { load_filter(wp - 8); load_filter(wp - 6); }
    }
    __syncwarp();
  }
  auto load_wm = [&](int u) {
    if (wp > 8 && l == 0) {
      mbar_expect(full0 + 8 * B_WM, 6144);
      tma2d(sbase + O_NRM + (wp - 9) * 6144, &maps.wm, 16 * u, 192 * (wp - 9), full0 + 8 * B_WM);
    }
    __syncwarp();
  };
  if (R >= 0) {
    const int ln0 = wg < 2 ? 2 * wp : 8 + wp;
    const int nl = min(wg < 2 ? 2 : 1, DF_ - col0 - ln0);
    uint4 cf[2][4], G[4];
#pragma unroll
    for (int i = 0; i < 4; i++) {
      cf[0][i] = __ldg(p.tab + TB_P2 + i * 32 + l);
      cf[1][i] = __ldg(p.tab + TB_P2 + (pi ? i : 4 + i) * 32 + l);
      G[i] = __ldg(p.tab + TB_P2 + (8 + i) * 32 + l);
    }
    const uint32_t* zin = sc->z1 + (size_t)R * 5120;
    if (wp == 10) {
      wait_cnt(&sc->cnt[C_Z1 + 32 * (pi >> 2)], 128 * ep);
      if (l == 0) {
        TS(12);
        mbar_expect(full0 + 8 * B_Z1, 20480);
        bulk_ld(sbase + O_P2, zin, 20480, full0 + 8 * B_Z1);
      }
      __syncwarp();
    }
    mbar_wait(full0 + 8 * B_FLT, 0);
    CK(9);
    float wn[16], wc[16];
#pragma unroll 1
    for (int ln = nl - 1; ln >= 0; ln--) {
      const int col = col0 + ln0 + ln, k2 = (57 * col) & 63;
      const bool cj = k2 > 32 || (k2 == 32 && col != 288);
      const float nr = ((col & 31) == 0 && col != 0 && col != 288 ? 0.5f : 1.0f) / ((float)S_ * D_), ni = cj ? -nr : nr;
#pragma unroll
      for (int i = 0; i < 16; i++) wn[i] = wc[i];
#pragma unroll
      for (int cl = 0; cl < 2; cl++) {
        const int v = cl ^ (cj && pi), e = ((v ? xv : xu) & 15) + ln0 + ln, sh = e < 32 ? 6 : 5;
        const uint32_t base = sbase + O_RAW + v * 12288 + (e < 32 ? 2 * e : 8192 - 64 + 2 * e), msk = e < 32 ? 0x30 : 0x10;
        const int dm = v ? (cj || pi ? -1 : 0) : 0;
#pragma unroll
        for (int tt = 0; tt < 4; tt++) {
          const int kc = g + 64 * (tt >> 1) + 16 * t + 8 * (tt & 1);
          uint32_t a = base + ((((cj ? -kc : kc) + dm) & 127) << sh);
          a ^= (a >> 3) & msk;
          wc[4 * tt + 2 * cl] = lds_bf(a) * nr; wc[4 * tt + 2 * cl + 1] = lds_bf(a + 24576) * ni;
        }
      }
    }
    const float al = pi ? 1.0f : 0.0f;
    CK(10);
    uint32_t off = pin(l * 160 + ((ln0 ^ (g & 3)) << 3));
    mbar_wait(full0 + 8 * B_Z1, 0);
    CK(11);
    if (tid == 0) TS(8);
    if (wg == 2) load_wm(72 + cta);
#pragma unroll 1
    for (int ln = 0; ln < nl; ln++, off ^= 8) {
      uint2 v[4];
#pragma unroll
      for (int i = 0; i < 4; i++) v[i] = lds2(sbase + O_P2 + off + i * 5120);
      if (__builtin_expect(any((diff2(v[0].x, v[1].x, tag1) | diff2(v[2].x, v[3].x, tag1)) & 1), 0)) {
        FAILCNT(0);
        int it = 0;
        do {
#pragma unroll
          for (int i = 0; i < 4; i++) v[i] = ld_rlx2(reinterpret_cast<const uint8_t*>(zin) + off + i * 5120);
        } while (any((diff2(v[0].x, v[1].x, tag1) | diff2(v[2].x, v[3].x, tag1)) & 1) && ++it < SPIN_MAX);
      }
      float d[4][4];
      uint32_t A[8];
#pragma unroll
      for (int h = 0; h < 2; h++) {
        mma16<false>(d[2 * h], cf[0][0].x, cf[0][0].y, cf[0][0].z, cf[0][0].w, v[h].x, v[2 + h].x);
        mma16<false>(d[2 * h + 1], cf[1][0].x, cf[1][0].y, cf[1][0].z, cf[1][0].w, v[h].y, v[2 + h].y);
      }
#pragma unroll
      for (int h = 0; h < 2; h++)
#pragma unroll
        for (int L = 0; L < 2; L++) {
          const uint4 tw = cf[L][2 + h];
          const float* z = d[2 * h + L];
          const float2 z0 = cmul(make_float2(z[0], z[2]), make_float2(__uint_as_float(tw.x), __uint_as_float(tw.y)));
          const float2 z1 = cmul(make_float2(z[1], z[3]), make_float2(__uint_as_float(tw.z), __uint_as_float(tw.w)));
          A[4 * h + L] = pack_bf16(z0.x, z0.y); A[4 * h + 2 + L] = pack_bf16(z1.x, z1.y);
        }
#pragma unroll
      for (int tt = 0; tt < 4; tt++) {
        mma16<false>(d[tt], A[0], A[1], A[2], A[3], G[tt].x, G[tt].y);
        mma16<true>(d[tt], A[4], A[5], A[6], A[7], G[tt].z, G[tt].w);
      }
#pragma unroll
      for (int tt = 0; tt < 4; tt++) {
        const float ar = d[tt][0], aj = d[tt][1], br = d[tt][2], bj = d[tt][3];
        const float2 y1 = cmul(make_float2(fmaf(-al, bj, ar), fmaf(al, br, aj)), make_float2(wc[4 * tt], wc[4 * tt + 1]));
        const float2 y2 = cmul(make_float2(fmaf(al, ar, bj), fmaf(al, aj, -br)), make_float2(wc[4 * tt + 2], wc[4 * tt + 3]));
        A[2 * tt] = pack_bf16(fmaf(al, y2.x, y1.x), fmaf(-al, y2.y, -y1.y));
        A[2 * tt + 1] = pack_bf16(fmaf(al, y1.y, -y2.y), fmaf(al, y1.x, -y2.x));
      }
#pragma unroll
      for (int i = 0; i < 16; i++) wc[i] = wn[i];
#pragma unroll
      for (int tt = 0; tt < 4; tt++) {
        mma16<false>(d[tt], A[0], A[1], A[2], A[3], G[tt].x, G[tt].y);
        mma16<true>(d[tt], A[4], A[5], A[6], A[7], G[tt].z, G[tt].w);
      }
#pragma unroll
      for (int h = 0; h < 2; h++)
#pragma unroll
        for (int L = 0; L < 2; L++) {
          const uint4 tw = cf[L][2 + h];
          const float2 z0 = cmul(make_float2(d[2 * h][2 * L], d[2 * h][2 * L + 1]), make_float2(__uint_as_float(tw.x), __uint_as_float(tw.y)));
          const float2 z1 = cmul(make_float2(d[2 * h + 1][2 * L], d[2 * h + 1][2 * L + 1]), make_float2(__uint_as_float(tw.z), __uint_as_float(tw.w)));
          A[4 * h + 2 * L] = movm(pack_bf16(z0.x, z1.x)); A[4 * h + 2 * L + 1] = movm(pack_bf16(z0.y, z1.y));
        }
#pragma unroll
      for (int h = 0; h < 2; h++) {
        mma16<false>(d[0], cf[0][1].x, cf[0][1].y, cf[0][1].z, cf[0][1].w, A[4 * h], A[4 * h + 1]);
        mma16<false>(d[1], cf[1][1].x, cf[1][1].y, cf[1][1].z, cf[1][1].w, A[4 * h + 2], A[4 * h + 3]);
#pragma unroll
        for (int e = 0; e < 2; e++)
          sts2(sbase + O_P2 + off + (2 * h + e) * 5120, set_tag(pack_bf16(d[0][e], d[0][2 + e]), tag1), pack_bf16(d[1][e], d[1][2 + e]));
      }
      CK(12 + ln);
    }
    fence_async_smem();
    if (wp) bar_arrive(6, NTHR);
    else {
      bar_sync(6, NTHR);
      if (l == 0) {
        tma_st2d(&maps.z2, sbase + O_P2, 40 * R, 0);
        HW();
        red_add(&sc->cnt[C_Z2], 1);
        TS(9);
      }
      __syncwarp();
    }
  }
  if (wg == 2) {
#pragma unroll 1
    for (int u = 72 + cta, k = 0; u < 216; u += NCTA, k ^= 1) {
      if (R < 0) { fence_async_smem(); bar_sync(4, 128); load_wm(u); }
      mbar_wait(full0 + 8 * B_WM, k);
      float acc[8] = {0.f, 0.f, 0.f, 0.f, 0.f, 0.f, 0.f, 0.f};
#pragma unroll 1
      for (int i = 0; i < 9; i++) mod_fma(acc, __uint_as_float(lds(red + 512 + ((t128 >> 1) + 64 * i) * 4)), lds4(sbase + O_NRM + t128 * 16 + i * 2048));
      mod_finish(p, acc, u, t128, red + 256 - 256 * k, tag16);
    }
    fence_async_smem();
    CK(13);
  }

  const int grp = cta / 11, m1 = cta - 11 * grp;
  const bool helper = (m1 & 3) == 3;
  const int f1 = 384 * grp + (helper ? 192 : 128) * (m1 >> 2);
  const int d1 = 160 * (m1 & 3), flip = m1 >= 7;
  const int a1bytes = helper ? 24576 : 16384;
  auto load_a1 = [&](int st, int kb) {
    mbar_expect(full0 + 8 * st, STAGE);
    tma4d_ef(sbase + st * STAGE, helper ? &maps.w1b : &maps.w1a, 4 * (kb >> 3), 16 * (kb & 7), f1 >> 6, full0 + 8 * st);
  };

  if (rows) {
#pragma unroll
    for (int kk = 0; kk < 4; kk++) af[kk] = __ldg(p.tab + TB_E + kk * 128 + t128);
    uint32_t tb[4], sy[6];
#pragma unroll
    for (int i = 0; i < 4; i++) tb[i] = pack_bf16(tmat(cta, 2 * t + 8 * (i & 1), 8 * (i >> 1) + g), tmat(cta, 2 * t + 8 * (i & 1) + 1, 8 * (i >> 1) + g));
#pragma unroll
    for (int i = 0; i < 6; i++) {
      const int rr = 16 * (wp & 3) + g + 8 * (i & 1);
      sy[i] = pin(sbase + O_Y + (t * 584 + 64 * ((3 * wg + (i >> 1) + 63 - rr) % 9) + rr) * 4);
    }
#pragma unroll
    for (int i = 0; i < 4; i++) tb[i] = pin(tb[i]);
    const int slot = 4 * (cta >> 4) + ((cta >> 1) & 3) + 32 * (2 * ((cta >> 3) & 1) + (cta & 1));
    const uint32_t* zin = sc->z2 + (size_t)slot * 4800;
    if (wg == 2) {
      {
        uint4 v[4];
        const int i3 = min(t128 + 384, 431);
        int it = 0;
        while (true) {
          uint32_t bad = 0;
#pragma unroll
          for (int k = 0; k < 4; k++) v[k] = ld_rlx4(sc->mod + 2 * D_ + 4 * (k < 3 ? t128 + 128 * k : i3));
#pragma unroll
          for (int k = 0; k < 4; k++) {
            v[k].x ^= tag16; v[k].y ^= tag16; v[k].z ^= tag16; v[k].w ^= tag16;
            bad |= v[k].x | v[k].y | v[k].z | v[k].w;
          }
          if (!any(bad & 0xffffu) || ++it > SPIN_MAX) break;
        }
#pragma unroll
        for (int k = 0; k < 4; k++) sts4(sbase + O_MOD + 16 * (k < 3 ? t128 + 128 * k : i3), v[k].x, v[k].y, v[k].z, v[k].w);
      }
      CK(14);
      mbar_wait(full0 + 8 * B_Z2, 0);
      if (l == 0) {
        load_a1(wp - 8, wp - 8);
        if (wp > 8 && wp - 8 < NG1) prefetch_l2(reinterpret_cast<const uint8_t*>(p.w1) + (size_t)(128 * (4 * ((wp - 8) >> 1) + (cta >> 5)) + 64 * (wp & 1) + 2 * (cta & 31)) * (2 * F_), 4 * F_);
      }
      __syncwarp();
    } else {
      uint32_t lo[9];
#pragma unroll
      for (int k1 = 0; k1 < 9; k1++) lo[k1] = pin(sbase + O_IN + line_off(k1, kap, 4 * wg + t, (cta >> 4) & 3));
      const uint32_t lx = pin(lo[0] + (kap ? 0 : 288 * 8));
      const uint32_t sb3 = pin(sbase + O_B3 + wg * 1024 + (l >> 4) * 2048 + (2 * (kap & 24) + (l & 15)) * 16);
      CK(14);
      if (wp == 0) {
        wait_cnt(&sc->cnt[C_Z2], 120 * ep);
        if (l == 0) {
          TS(14);
          mbar_expect(full0 + 8 * B_Z2, 19200);
          bulk_ld(sbase + O_IN, zin, 19200, full0 + 8 * B_Z2);
        }
        __syncwarp();
      }
      mbar_wait(full0 + 8 * B_Z2, 0);
      CK(15);
      if (tid == 0) TS(11);
      uint2 v[10];
      uint32_t bad = 0;
#pragma unroll
      for (int k1 = 0; k1 < 10; k1++) v[k1] = lds2(k1 < 9 ? lo[k1] : lx);
#pragma unroll
      for (int k1 = 0; k1 < 10; k1 += 2) bad |= diff2(v[k1].x, v[k1 + 1].x, tag1);
      if (__builtin_expect(any(bad & 1), 0)) {
        FAILCNT(1);
        int it = 0;
        do {
          bad = 0;
#pragma unroll
          for (int k1 = 0; k1 < 10; k1++) v[k1] = ld_rlx2(reinterpret_cast<const uint8_t*>(zin) + ((k1 < 9 ? lo[k1] : lx) - (sbase + O_IN)));
#pragma unroll
          for (int k1 = 0; k1 < 10; k1 += 2) bad |= diff2(v[k1].x, v[k1 + 1].x, tag1);
        } while (any(bad & 1) && ++it < SPIN_MAX);
      }
      float2 za[9], zb[9];
#pragma unroll
      for (int i = 0; i < 9; i++) { za[i] = make_float2(bf_lo(v[i].x), bf_hi(v[i].x)); zb[i] = make_float2(bf_lo(v[i].y), bf_hi(v[i].y)); }
      if (kap == 0) {
#pragma unroll
        for (int k = 1; k < 5; k++) {
          float2 a = za[k], b = za[9 - k];
          za[k] = make_float2(a.x - b.y, a.y + b.x); za[9 - k] = make_float2(a.x + b.y, b.x - a.y);
          a = zb[k]; b = zb[9 - k];
          zb[k] = make_float2(a.x - b.y, a.y + b.x); zb[9 - k] = make_float2(a.x + b.y, b.x - a.y);
        }
        za[0].y = bf_lo(v[9].x); zb[0].y = bf_lo(v[9].y);
      }
      __syncwarp();
      dft9(za); dft9(zb);
#pragma unroll
      for (int n = 0; n < 8; n += 2) {
        const int i0 = (9 - n) % 9, i1 = 8 - n;
        stmatrix4(sb3 + n * 2048, pack_bf16(za[i0].x, zb[i0].x), pack_bf16(za[i0].y, zb[i0].y), pack_bf16(za[i1].x, zb[i1].x), pack_bf16(za[i1].y, zb[i1].y));
      }
      stmatrix2(sb3 + 8 * 2048, pack_bf16(za[1].x, zb[1].x), pack_bf16(za[1].y, zb[1].y));
      fence_async_smem();
    }
    CK(16);
    __syncthreads();
    CK(17);
    float acc[24];
    const uint32_t db = (((sbase + O_B3 + wg * 6144) & 0x3FFFF) >> 4) | ((128 >> 4) << 16);
    wg_fence();
#pragma unroll
    for (int kk = 0; kk < 4; kk++) wgmma_rs_48(acc, af[kk].x, af[kk].y, af[kk].z, af[kk].w, db + kk * 16, 1024 >> 4, kk);
    wg_commit();
    uint32_t ga[9];
    uint2 sh[9], sw[9];
    if (wg < 2) {
#pragma unroll
      for (int i = 0; i < 9; i++) {
        const uint2 v = lds2(sbase + O_MOD + (64 * i + 2 * l) * 4);
        ga[i] = __byte_perm(v.x, v.y, 0x7632);
        sh[i] = lds2(sbase + O_MOD + (D_ + 64 * i + 2 * l) * 4);
        sw[i] = lds2(sbase + O_MOD + (2 * D_ + 64 * i + 2 * l) * 4);
      }
    }
    wg_wait<0>();
    reg_fence(acc);
    CK(18);
#pragma unroll
    for (int i = 0; i < 3; i++) {
      const float* a = &acc[8 * i];
      const uint32_t a0 = pack_bf16(a[0], a[1]), a1 = pack_bf16(a[2], a[3]), a2 = pack_bf16(a[4], a[5]), a3 = pack_bf16(a[6], a[7]);
#pragma unroll
      for (int jh = 0; jh < 2; jh++) {
        float y[4];
        mma16<false>(y, a0, a1, a2, a3, tb[2 * jh], tb[2 * jh + 1]);
        sts(sy[2 * i] + jh * (4 * 584 * 4), pack_bf16(y[0], y[1]));
        sts(sy[2 * i + 1] + jh * (4 * 584 * 4), pack_bf16(y[2], y[3]));
      }
    }
    CK(19);
    if (wg == 2) bar_arrive(7, NTHR);
    else {
      bar_sync(7, NTHR);
      CK(20);
      float a[18], b[18];
#pragma unroll
      for (int i = 0; i < 9; i++) {
        const uint2 y = lds2(sbase + O_Y + (wp * 584 + 64 * i + 2 * l) * 4);
        xr[i] = hfma2(ga[i], __byte_perm(y.x, y.y, 0x5410), xr[i]);
        xr[9 + i] = hfma2(ga[i], __byte_perm(y.x, y.y, 0x7632), xr[9 + i]);
        a[2 * i] = bf_lo(xr[i]); a[2 * i + 1] = bf_hi(xr[i]); b[2 * i] = bf_lo(xr[9 + i]); b[2 * i + 1] = bf_hi(xr[9 + i]);
      }
      float oa, ra, ob, rb;
      ln_stats2(a, b, 1.0f, oa, ra, ob, rb);
      CK(21);
#pragma unroll
      for (int i = 0; i < 9; i++) {
        const float c0 = __uint_as_float(sw[i].x), c1 = __uint_as_float(sw[i].y), s0 = __uint_as_float(sh[i].x), s1 = __uint_as_float(sh[i].y);
        a[2 * i] = fmaf(fmaf(a[2 * i], ra, oa), c0, s0); a[2 * i + 1] = fmaf(fmaf(a[2 * i + 1], ra, oa), c1, s1);
        b[2 * i] = fmaf(fmaf(b[2 * i], rb, ob), c0, s0); b[2 * i + 1] = fmaf(fmaf(b[2 * i + 1], rb, ob), c1, s1);
      }
      ln_stats2(a, b, 0.5f, oa, ra, ob, rb);
      CK(22);
      const uint32_t sh3 = sbase + O_B3 + (wp >> 1) * 4608 + (l >> 4) * 256 + (wp & 1) * 128 + ((((l >> 2) ^ (2 * cta + (wp & 1))) & 3) << 4) + (l & 3) * 4;
#pragma unroll
      for (int i = 0; i < 9; i++) {
        sts(sh3 + i * 512, pack_bf16(fmaf(a[2 * i], ra, oa), fmaf(a[2 * i + 1], ra, oa)));
        sts(sh3 + i * 512 + 64, pack_bf16(fmaf(b[2 * i], rb, ob), fmaf(b[2 * i + 1], rb, ob)));
      }
      fence_async_smem();
      if (wp == 0) CKX(0);
      bar_arrive(8 + wg, 160);
      CK(23);
    }
  } else __syncthreads();

  const bool g2 = cta < 130 && (cta >> 1) != 56;
  const int z2 = cta < 112 ? cta : cta - 2, r = z2 >> 6;
  const int s2 = 128 * ((z2 >> 2) & 15), d2 = 144 * (z2 & 3);
  constexpr int XST = (33 + 36 - JSK - 1) % NST;
  constexpr int ST0 = (32 - JSK - 1) % NST, ST1 = 31 % NST;

  if (wg == 2) {
    asm volatile("setmaxnreg.dec.sync.aligned.u32 40;");
    if (wp == 8) {
      int st = rows ? 4 : 0, ph = 1;
#pragma unroll 1
      for (int kb = st; kb < 32; kb++) {
        if (rows && (kb >> 1) == 2) mbar_wait(full0 + 8 * (B_S4 - 4 + kb), 0);
        mbar_wait(empty0 + 8 * st, ph);
        if (l == 0) {
          load_a1(st, kb);
          if (kb >= PF2K && kb < PF2K + PF2 && g2)
            prefetch_l2(reinterpret_cast<const uint8_t*>(p.w2) + (size_t)(36 * r + kb2_order(kb - PF2K)) * 262144 + (z2 & 63) * 4096, 4096);
        }
        __syncwarp();
        ring_next<false>(st, ph);
      }
      if (g2) {
        st++;
#pragma unroll 1
        for (int i = 0; i < 36; i++) {
          if (i == HOLDA) mbar_wait(full0 + 8 * B_GO, 0);
          mbar_wait(empty0 + 8 * st, ph);
          if (l == 0) {
            mbar_expect(full0 + 8 * st, 16384 + 18432);
            tma3d_ef(sbase + st * STAGE, &maps.w2, 64 * (36 * r + kb2_order(i)), s2 >> 6, full0 + 8 * st);
          }
          __syncwarp();
          ring_next<true>(st, ph);
        }
      }
    } else if (wp >= 10) {
      const int sw = wp - 10;
      if (rows) {
        bar_sync(8 + sw, 160);
        if (!sw) CKX(1);
        if (l == 0) mbar_arrive(full0 + 8 * B_S4);
        if (sw && H3W >= 0) { mbar_wait(full0 + 8 * H3W, 0); CKX(7); }
        if (l == 0) {
          tma_st3d(&maps.h3, sbase + O_B3 + sw * 9216, 64 * (cta & 15), 18 * (cta >> 4), 2 * sw);
          if (!sw) CKX(2);
          bulk_commit_wait();
          if (!sw) CKX(3);
          mbar_arrive(full0 + 8 * B_S5);
          asm volatile("fence.acq_rel.gpu;" ::: "memory");
          red_add(&sc->cnt[C_H3 + (cta >> 4) + 8 * sw], 1);
          if (!sw) CKX(4);
          TS(sw ? 24 : 13);
        }
        __syncwarp();
      }
      if (sw && g2) {
        mbar_wait(full0 + 8 * 5, 0);
#pragma unroll 1
        for (int i = 0; i < 36; i++) { sc->part[z2 * 1152 + 32 * i + l] = make_uint4(tag1 ^ 1, 0, 0, 0); __nanosleep(100); }
        __syncwarp();
      }
      const uint32_t stg = sbase + (sw ? ST1 : ST0) * STAGE;
      const int kbA = (f1 >> 6) + (helper ? 2 : 1) * (sw ^ flip), kbB = helper ? (f1 >> 6) + 1 : kbA;
      const int dB = helper ? d1 + 32 * sw : d1 + 96;
      bar_sync(11 + sw, 160);
      if (l == 0) { TS(sw ? 31 : 30); bulk_st(sc->u + ((size_t)kbA * D_ + d1) * 128, stg, 96 * 128); }
      __syncwarp();
      bar_sync(13 + sw, 160);
      if (l == 0) {
        bulk_st(sc->u + ((size_t)kbB * D_ + dB) * 128, stg + 96 * 128, helper ? 32 * 128 : 64 * 128);
        if (helper) bulk_st(sc->u + ((size_t)kbB * D_ + d1 + 64 + 16 * sw) * 128, stg + 128 * 128, 16 * 128);
        bulk_commit_wait();
        mbar_arrive(empty0 + 8 * (sw ? ST1 : ST0));
        if (sw == 0) TS(26);
        asm volatile("fence.acq_rel.gpu;" ::: "memory");
        red_add(&sc->cnt[C_U + kbA], 2);
        if (helper) red_add(&sc->cnt[C_U + kbB], 1);
        TS(sw ? 23 : 17);
      }
      __syncwarp();
    } else {
      uint64_t ready = 0;
      int st = 0, ph = 1;
#pragma unroll 1
      for (int kb = 0; kb < 32; kb++) {
        if (rows && (kb >> 1) == 2) mbar_wait(full0 + 8 * (B_S4 - 4 + kb), 0);
        mbar_wait(empty0 + 8 * st, ph);
        wait_flags(sc->cnt + C_H3, 32, (kb & 7) + ((kb >> 1) & 8), 16 * ep, ready);
        if (kb == 0) CKX(5);
        if (l == 0) bulk_ld(sbase + st * STAGE + a1bytes, sc->h3 + ((size_t)(kb * 18 + (d1 >> 5)) << 12), STAGE - a1bytes, full0 + 8 * st);
        if (kb == 0) CKX(6);
        if (kb == 5) CKX(8);
        if (kb == 16) CKX(9);
        ring_next<false>(st, ph);
      }
      if (g2) {
        ready = 0;
        st++;
#pragma unroll 1
        for (int i = 0; i < 72; i++) {
          if (i == 36) ready = 0;
          const int kb = kb2_order(i < 36 ? i : i - 36), hf = r ^ (i >= 36);
          if (i <= 36) mbar_wait(empty0 + 8 * st, ph);
          wait_flags(sc->cnt + C_U + 36 * hf, 36, kb, 8 * ep, ready);
          if (i < 36) {
            if (l == 0) {
              bulk_ld(sbase + st * STAGE + 16384, sc->u + ((size_t)(36 * r + kb) * D_ + d2) * 128, 18432, full0 + 8 * st);
              if (i == GOAT) mbar_arrive(full0 + 8 * B_GO);
            }
            ring_next<true>(st, ph);
          } else if (ready == ~0ull) break;
        }
        if (l == 0) mbar_expect(full0 + 8 * XST, 18432);
        __syncwarp();
        if (l < 3) tma2d(sbase + XST * STAGE + 18432 + l * 6144, &maps.x1, d2 + 48 * l, s2 + 64 * (r ^ 1), full0 + 8 * XST);
        __syncwarp();
      }
    }
  } else {
    asm volatile("setmaxnreg.inc.sync.aligned.u32 232;");
    const int wgu = wg;
    constexpr uint32_t sb4 = sbase >> 4;
    const int w = wp & 3;
    Ring rg = {0, 0};
    uint32_t* const x1p = sc->x1 + (size_t)(cta + 256 * wp) * 288 + l;
    float acc[80];
    constexpr uint32_t LA = (8192 >> 4) << 16, LB = (4096 >> 4) << 16;
    {
      const int fa = f1 + (helper ? 128 : 64) * (wg ^ flip) + 16 * w + g, fb = helper ? f1 + 64 + 16 * w + g : fa;
      const float a0 = 0.5f * __bfloat162float(p.b1[fa]), a1 = 0.5f * __bfloat162float(p.b1[fa + 8]);
      const float b0 = 0.5f * __bfloat162float(p.b1[fb]), b1 = 0.5f * __bfloat162float(p.b1[fb + 8]);
#pragma unroll
      for (int i = 0; i < 80; i++) acc[i] = i < 48 ? ((i & 2) ? a1 : a0) : ((i & 2) ? b1 : b0);
      reg_fence(acc);
    }
    if (!helper) gemm_main<0>(acc, sb4 + (wgu ^ flip) * 512 + LA, 0, sb4 + 1024 + LB, 0, wgu, rg, x1p, xr);
    else {
      float ac2[80];
#pragma unroll
      for (int i = 0; i < 72; i++) asm volatile("mov.b32 %0, %1;" : "=f"(ac2[i]) : "f"(acc[i]));
      gemm_main<1>(ac2, sb4 + (wgu ^ flip) * 1024 + LA, sb4 + 512 + LA, sb4 + 1536 + LB, sb4 + 1536 + (wgu ? 256 + LB + (2 << 16) : 2 * LB), wgu, rg, x1p, xr);
#pragma unroll
      for (int i = 0; i < 72; i++) asm volatile("mov.b32 %0, %1;" : "=f"(acc[i]) : "f"(ac2[i]));
    }
    if (t128 == 0) TS(wg ? 16 : 6);
    {
      const int mi = l >> 3, rr = l & 7;
      const uint32_t ad = sbase + (wg ? ST1 : ST0) * STAGE + (8 * (mi >> 1) + rr) * 128 + (((2 * w + (mi & 1)) ^ rr) << 4);
      float z[2][16];
#pragma unroll
      for (int j = -1; j <= 5; j++) {
        if (j >= 1) {
          const float* a = &acc[16 * (j - 1)];
          const float* tt = z[(j - 1) & 1];
#pragma unroll
          for (int h = 0; h < 16; h += 8)
            stmatrix4t(ad + (2 * (j - 1) + (h >> 3)) * 2048, pack_bf16(fmaf(a[h], tt[h], a[h]), fmaf(a[h + 1], tt[h + 1], a[h + 1])),
                       pack_bf16(fmaf(a[h + 2], tt[h + 2], a[h + 2]), fmaf(a[h + 3], tt[h + 3], a[h + 3])),
                       pack_bf16(fmaf(a[h + 4], tt[h + 4], a[h + 4]), fmaf(a[h + 5], tt[h + 5], a[h + 5])),
                       pack_bf16(fmaf(a[h + 6], tt[h + 6], a[h + 6]), fmaf(a[h + 7], tt[h + 7], a[h + 7])));
        }
        if (j >= 0 && j < 5) {
#pragma unroll
          for (int e = 0; e < 16; e++) asm("tanh.approx.f32 %0, %0;" : "+f"(z[j & 1][e]));
        }
        if (j < 4) {
#pragma unroll
          for (int e = 0; e < 16; e++) z[(j + 1) & 1][e] = gelu_arg(acc[16 * (j + 1) + e]);
        }
        if (j == 3 || j == 5) { fence_async_smem(); asm volatile("bar.arrive %0, 160;" ::"r"((j == 3 ? 11 : 13) + wgu) : "memory"); }
        if (j < 5) {
          if (j >= 0) reg_fence(z[j & 1]);
          if (j < 4) reg_fence(z[(j + 1) & 1]);
          if (__builtin_expect(wp == 0x7ffffff0 + j, 0)) __trap();
          reg_fence(acc);
        }
      }
      if (t128 == 0) TS(wg ? 29 : 28);
    }
    if (g2) {
      const int mb = wgu ^ r;
      uint32_t gb[18];
      {
        float a0 = 0.f, a1 = 0.f;
        if (wgu) {
          a0 = __bfloat162float(p.b2[s2 + 64 * mb + 16 * w + g]); a1 = __bfloat162float(p.b2[s2 + 64 * mb + 16 * w + 8 + g]);
          int it = 0;
          uint32_t bad;
          do {
            bad = 0;
#pragma unroll
            for (int i = 0; i < 18; i++) {
              const uint2 v = ld_rlx2(sc->mod + 5 * D_ + d2 + 8 * i + 2 * t);
              bad |= (v.x ^ tag16) | (v.y ^ tag16);
              gb[i] = __byte_perm(v.x, v.y, 0x7632);
            }
          } while (any(bad & 0xffffu) && ++it < SPIN_MAX);
        }
#pragma unroll
        for (int i = 0; i < 72; i++) acc[i] = (i & 2) ? a1 : a0;
      }
      rg.st++;
      gemm_main<3>(acc, sb4 + mb * 512 + LA, 0, sb4 + 1024 + (1 << 16), 0, wgu, rg, x1p, xr);
      if (t128 == 0) TS(wg ? 20 : 19);
      const uint32_t sx = sbase + XST * STAGE;
      if (wgu == 0) {
        uint4* dst = sc->part + z2 * 1152 + t128;
#pragma unroll
        for (int j = 0; j < 9; j++) {
          const float* a = &acc[8 * j];
          dst[j * 128] = make_uint4(set_tag(pack_bf16(a[0], a[1]), tag1), pack_bf16(a[2], a[3]), pack_bf16(a[4], a[5]), pack_bf16(a[6], a[7]));
        }
        if (tid == 0) TS(21);
        const uint4* src = sc->part + (z2 ^ 64) * 1152 + t128;
        uint4 v[9];
        uint32_t bad;
        int it = 0;
        do {
#pragma unroll
          for (int j = 0; j < 9; j++) v[j] = ld_rlx4(src + j * 128);
          bad = v[8].x ^ tag1;
#pragma unroll
          for (int j = 0; j < 8; j += 2) bad |= diff2(v[j].x, v[j + 1].x, tag1);
        } while (any(bad & 1) && ++it < SPIN_MAX);
#pragma unroll
        for (int j = 0; j < 9; j++) sts4(sx + t128 * 16 + j * 2048, v[j].x, v[j].y, v[j].z, v[j].w);
        bar_arrive(2 + w, 64);
        if (w == 0) {
#pragma unroll 1
          for (int i = 0; i < 3; i++) {
            bar_sync(11 + i, 160);
            if (l == 0) tma_st2d(&maps.out, sx + 18432 + i * 6144, d2 + 48 * i, s2 + 64 * (r ^ 1));
            __syncwarp();
          }
          if (l == 0) { bulk_commit_wait_read(); TS(22); }
          __syncwarp();
        }
      } else {
        mbar_wait(full0 + 8 * XST, rg.ph);
        bar_sync(2 + w, 64);
        if (t128 == 0) TS(5);
        if (tid == 128 && cta == 0) sc->cnt[C_EP] = ep;
        const uint32_t xa = sx + 18432 + (16 * w + (l & 15)) * 96 + (l >> 4) * 16;
#pragma unroll
        for (int c = 0; c < 3; c++) {
          uint32_t pv[3][4], xv[3][4];
#pragma unroll
          for (int j = 0; j < 3; j++) {
            asm volatile("ld.shared.v4.b32 {%0,%1,%2,%3}, [%4];" : "=r"(pv[j][0]), "=r"(pv[j][1]), "=r"(pv[j][2]), "=r"(pv[j][3]) : "r"(sx + t128 * 16 + (3 * c + j) * 2048) : "memory");
            asm volatile("ldmatrix.sync.aligned.m8n8.x4.shared.b16 {%0,%1,%2,%3}, [%4];" : "=r"(xv[j][0]), "=r"(xv[j][1]), "=r"(xv[j][2]), "=r"(xv[j][3]) : "r"(xa + c * 6144 + j * 32) : "memory");
          }
#pragma unroll
          for (int j = 0; j < 3; j++) {
            const float* a = &acc[8 * (3 * c + j)];
            uint32_t o[4];
#pragma unroll
            for (int e = 0; e < 4; e++)
              o[e] = hadd2(xv[j][e], hmul2(gb[2 * (3 * c + j) + (e >> 1)], pack_bf16(a[2 * e] + bf_lo(pv[j][e]), a[2 * e + 1] + bf_hi(pv[j][e]))));
            stmatrix4(xa + c * 6144 + j * 32, o[0], o[1], o[2], o[3]);
          }
          fence_async_smem();
          asm volatile("bar.arrive %0, 160;" ::"r"(11 + c) : "memory");
        }
        if (t128 == 0) TS(7);
        __syncwarp();
      }
    }
  }
}

typedef CUresult (*EncodeFn)(CUtensorMap*, CUtensorMapDataType, cuuint32_t, void*, const cuuint64_t*, const cuuint64_t*, const cuuint32_t*,
                             const cuuint32_t*, CUtensorMapInterleave, CUtensorMapSwizzle, CUtensorMapL2promotion, CUtensorMapFloatOOBfill);

struct Dim { cuuint64_t n, stride; cuuint32_t box; };
template <int RANK>
void make_map(EncodeFn enc, CUtensorMap* m, bool words, int swz, const void* ptr, const Dim (&d)[RANK]) {
  cuuint64_t gd[RANK], gs[RANK];
  cuuint32_t bx[RANK], es[RANK];
  for (int i = 0; i < RANK; i++) { gd[i] = d[i].n; gs[i] = d[i].stride; bx[i] = d[i].box; es[i] = 1; }
  enc(m, words ? CU_TENSOR_MAP_DATA_TYPE_UINT32 : CU_TENSOR_MAP_DATA_TYPE_BFLOAT16, RANK, const_cast<void*>(ptr), gd, gs + 1, bx, es,
      CU_TENSOR_MAP_INTERLEAVE_NONE, static_cast<CUtensorMapSwizzle>(swz),
      swz == 3 ? CU_TENSOR_MAP_L2_PROMOTION_L2_256B : CU_TENSOR_MAP_L2_PROMOTION_NONE, CU_TENSOR_MAP_FLOAT_OOB_FILL_NONE);
}

}

extern "C" void kernel_launch(void* const* d_in, const int* in_sizes, int n_in, void* d_out, int out_size) {
  (void)in_sizes; (void)n_in; (void)out_size;
  static EncodeFn enc = nullptr;
  static void *sptr = nullptr, *tptr = nullptr;
  if (!enc) {
    void* f = nullptr; cudaDriverEntryPointQueryResult qr;
    cudaGetDriverEntryPoint("cuTensorMapEncodeTiled", &f, cudaEnableDefault, &qr);
    enc = reinterpret_cast<EncodeFn>(f);
    cudaFuncSetAttribute(fused_kernel, cudaFuncAttributeMaxDynamicSharedMemorySize, SMEM_BYTES);
    cudaGetSymbolAddress(&sptr, g_s);
    cudaGetSymbolAddress(&tptr, T_TAB);
  }
  Params p;
  p.x = (const __nv_bfloat16*)d_in[0]; p.wr = (const __nv_bfloat16*)d_in[1]; p.wi = (const __nv_bfloat16*)d_in[2];
  p.b1 = (const __nv_bfloat16*)d_in[5]; p.b2 = (const __nv_bfloat16*)d_in[7];
  p.c = (const __nv_bfloat16*)d_in[8]; p.wmod = (const __nv_bfloat16*)d_in[9];
  p.w1 = (const __nv_bfloat16*)d_in[4]; p.w2 = (const __nv_bfloat16*)d_in[6];
  p.s = static_cast<Scratch*>(sptr); p.tab = static_cast<const uint4*>(tptr);
  Maps maps;
  make_map<4>(enc, &maps.w1a, false, 3, p.w1, {{64, 0, 64}, {16, 128 * 2 * F_, 4}, {128, 2 * F_, 16}, {72, 128, 2}});
  make_map<4>(enc, &maps.w1b, false, 3, p.w1, {{64, 0, 64}, {16, 128 * 2 * F_, 4}, {128, 2 * F_, 16}, {72, 128, 3}});
  make_map<3>(enc, &maps.w2, false, 3, p.w2, {{64, 0, 64}, {F_, 2 * S_, 64}, {32, 128, 2}});
  make_map<2>(enc, &maps.x1, false, 0, p.s->x1, {{D_, 0, 48}, {S_, 2 * D_, 64}});
  make_map<2>(enc, &maps.out, false, 0, d_out, {{D_, 0, 48}, {S_, 2 * D_, 64}});
  make_map<2>(enc, &maps.z1, true, 0, p.s->z1, {{5120, 0, 40}, {120, 20480, 60}});
  make_map<2>(enc, &maps.z2, true, 0, p.s->z2, {{4800, 0, 40}, {128, 19200, 128}});
  for (int i = 0; i < 4; i++) make_map<2>(enc, &maps.wf[i], false, 2 - (i & 1), (i & 2) ? p.wi : p.wr, {{16 * DF_, 0, (i & 1) ? 16u : 32u}, {128, 32 * DF_, 128}});
  make_map<2>(enc, &maps.wm, false, 0, p.wmod, {{6 * D_, 0, 16}, {D_, 12 * D_, 192}});
  make_map<3>(enc, &maps.h3, true, 0, p.s->h3, {{1024, 0, 64}, {144, 4096, 18}, {4, 144 * 4096, 2}});
  fused_kernel<<<NCTA, NTHR, SMEM_BYTES, cudaStreamPerThread>>>(p, maps);
}
```

```cpp
#include <cuda_runtime.h>
#include <cuda_bf16.h>
#include <cuda.h>
#include <stdint.h>

namespace {

constexpr int S_ = 2048, D_ = 576, DF_ = 289, F_ = 4608;
constexpr int NCTA = 132, NTHR = 384;
constexpr int STAGE = 36864, NST = 6;
constexpr uint32_t sbase = 1024, full0 = sbase + NST * STAGE, empty0 = full0 + 8 * NST, red = full0 + 256;
constexpr int SMEM_BYTES = NST * STAGE + 256 + 512 + 4 * D_ + 512;
constexpr int O_NRM = 0, O_B1 = 19456, O_Z1 = 38912, O_P2 = 59392;
constexpr int O_RAW = 4 * STAGE;
constexpr int O_IN = 4 * STAGE, O_Y = O_IN + 19456, O_B3 = O_IN + 38912, O_MOD = O_IN + 57344;

__device__ __align__(128) const uint32_t T_TAB[5632] = {
0x3f803f80,0xbf803f80,0x3f803f80,0xbf803f80,0x3f803f80,0xbf803f80,0x3f803f80,0xbf803f80,0x3f803f80,0xbf803f80,0x3f803f80,0xbf803f80,
0x3f803f80,0xbf803f80,0x3f803f80,0xbf803f80,0x3f7f3f80,0xbdc90000,0x3f223f35,0xbf46bf35,0x3f753f7b,0xbe95be48,0x3ef13f0e,0xbf62bf55,
0x3f623f6d,0xbef1bec4,0x3e953ec4,0xbf75bf6d,0x3f463f55,0xbf22bf0e,0x3dc93e48,0xbf7fbf7b,0x3f7b3f80,0xbe480000,0xbe480000,0xbf7bbf80,
0x3f553f6d,0xbf0ebec4,0xbf0ebec4,0xbf55bf6d,0x3f0e3f35,0xbf55bf35,0xbf55bf35,0xbf0ebf35,0x3e483ec4,0xbf7bbf6d,0xbf7bbf6d,0xbe48bec4,
0x3f753f80,0xbe950000,0xbf62bf35,0xbef1bf35,0x3f223f55,0xbf46bf0e,0xbf7fbf7b,0x3dc9be48,0x3dc93ec4,0xbf7fbf6d,0xbf46bf6d,0x3f223ec4,
0xbef1be48,0xbf62bf7b,0xbe95bf0e,0x3f753f55,0x3f6d3f80,0xbec40000,0xbf6dbf80,0x3ec40000,0x3ec43f35,0xbf6dbf35,0xbec4bf35,0x3f6d3f35,
0xbec40000,0xbf6dbf80,0x3ec40000,0x3f6d3f80,0xbf6dbf35,0xbec4bf35,0x3f6d3f35,0x3ec43f35,0x3f623f80,0xbef10000,0xbe95bf35,0x3f753f35,
0x3dc93f0e,0xbf7fbf55,0x3f223e48,0x3f463f7b,0xbf46bec4,0xbf22bf6d,0x3f7f3f6d,0xbdc93ec4,0xbf75bf7b,0x3e95be48,0x3ef13f55,0xbf62bf0e,
0x3f553f80,0xbf0e0000,0x3f0e0000,0x3f553f80,0xbe483ec4,0xbf7bbf6d,0x3f7b3f6d,0xbe483ec4,0xbf7bbf35,0xbe48bf35,0x3e483f35,0xbf7bbf35,
0xbf0ebf6d,0x3f553ec4,0xbf55bec4,0xbf0ebf6d,0x3f463f80,0xbf220000,0x3f7f3f35,0x3dc93f35,0xbef13e48,0xbf62bf7b,0x3e953f55,0xbf75bf0e,
0xbf75bf6d,0x3e95bec4,0xbf62bec4,0xbef1bf6d,0x3dc9bf0e,0x3f7f3f55,0xbf22bf7b,0x3f463e48,0x3f353f80,0xbf350000,0x3f353f80,0xbf350000,
0xbf350000,0xbf35bf80,0xbf350000,0xbf35bf80,0xbf35bf80,0x3f350000,0xbf35bf80,0x3f350000,0x3f350000,0x3f353f80,0x3f350000,0x3f353f80,
0x3f223f80,0xbf460000,0xbdc93f35,0xbf7fbf35,0xbf62be48,0xbef1bf7b,0xbf75bf55,0x3e95bf0e,0xbe95bf6d,0x3f753ec4,0x3ef1bec4,0x3f623f6d,
0x3f7f3f0e,0x3dc93f55,0x3f463f7b,0xbf223e48,0x3f0e3f80,0xbf550000,0xbf550000,0xbf0ebf80,0xbf7bbec4,0xbe48bf6d,0xbe48bf6d,0x3f7b3ec4,
0x3e48bf35,0x3f7b3f35,0x3f7b3f35,0xbe483f35,0x3f553f6d,0xbf0e3ec4,0xbf0e3ec4,0xbf55bf6d,0x3ef13f80,0xbf620000,0xbf75bf35,0x3e95bf35,
0xbf7fbf0e,0x3dc9bf55,0x3f46be48,0x3f223f7b,0x3f22bec4,0x3f463f6d,0x3dc93f6d,0xbf7fbec4,0x3e953f7b,0xbf75be48,0xbf62bf55,0x3ef1bf0e,
0x3ec43f80,0xbf6d0000,0xbec4bf80,0x3f6d0000,0xbf6dbf35,0x3ec4bf35,0x3f6d3f35,0xbec43f35,0x3f6d0000,0x3ec43f80,0xbf6d0000,0xbec4bf80,
0xbec43f35,0xbf6dbf35,0x3ec4bf35,0x3f6d3f35,0x3e953f80,0xbf750000,0x3ef1bf35,0x3f623f35,0xbf46bf55,0x3f22bf0e,0x3dc93f7b,0xbf7fbe48,
0x3f7f3ec4,0xbdc93f6d,0xbf22bf6d,0x3f46bec4,0xbf623e48,0xbef1bf7b,0x3f753f0e,0xbe953f55,0x3e483f80,0xbf7b0000,0x3f7b0000,0x3e483f80,
0xbf0ebf6d,0x3f55bec4,0xbf553ec4,0xbf0ebf6d,0x3f553f35,0xbf0e3f35,0x3f0ebf35,0x3f553f35,0xbf7bbec4,0x3e48bf6d,0xbe483f6d,0xbf7bbec4,
0x3dc93f80,0xbf7f0000,0x3f463f35,0xbf223f35,0xbe95bf7b,0x3f75be48,0xbf62bf0e,0x3ef1bf55,0x3ef13f6d,0xbf623ec4,0x3f753ec4,0xbe953f6d,
0xbf22bf55,0x3f46bf0e,0xbf7fbe48,0x3dc9bf7b,0x3f80,0xbf800000,0x3f80,0xbf800000,0xbf80,0x3f800000,0xbf80,0x3f800000,
0x3f80,0xbf800000,0x3f80,0xbf800000,0xbf80,0x3f800000,0xbf80,0x3f800000,0xbdc93f80,0xbf7f0000,0xbf463f35,0xbf22bf35,
0x3e95bf7b,0x3f753e48,0x3f62bf0e,0x3ef13f55,0xbef13f6d,0xbf62bec4,0xbf753ec4,0xbe95bf6d,0x3f22bf55,0x3f463f0e,0x3f7fbe48,0x3dc93f7b,
0xbe483f80,0xbf7b0000,0xbf7b0000,0x3e48bf80,0x3f0ebf6d,0x3f553ec4,0x3f553ec4,0xbf0e3f6d,0xbf553f35,0xbf0ebf35,0xbf0ebf35,0x3f55bf35,
0x3f7bbec4,0x3e483f6d,0x3e483f6d,0xbf7b3ec4,0xbe953f80,0xbf750000,0xbef1bf35,0x3f62bf35,0x3f46bf55,0x3f223f0e,0xbdc93f7b,0xbf7f3e48,
0xbf7f3ec4,0xbdc9bf6d,0x3f22bf6d,0x3f463ec4,0x3f623e48,0xbef13f7b,0xbf753f0e,0xbe95bf55,0xbec43f80,0xbf6d0000,0x3ec4bf80,0x3f6d0000,
0x3f6dbf35,0x3ec43f35,0xbf6d3f35,0xbec4bf35,0xbf6d0000,0x3ec4bf80,0x3f6d0000,0xbec43f80,0x3ec43f35,0xbf6d3f35,0xbec4bf35,0x3f6dbf35,
0xbef13f80,0xbf620000,0x3f75bf35,0x3e953f35,0x3f7fbf0e,0x3dc93f55,0xbf46be48,0x3f22bf7b,0xbf22bec4,0x3f46bf6d,0xbdc93f6d,0xbf7f3ec4,
0xbe953f7b,0xbf753e48,0x3f62bf55,0x3ef13f0e,0xbf0e3f80,0xbf550000,0x3f550000,0xbf0e3f80,0x3f7bbec4,0xbe483f6d,0x3e48bf6d,0x3f7bbec4,
0xbe48bf35,0x3f7bbf35,0xbf7b3f35,0xbe48bf35,0xbf553f6d,0xbf0ebec4,0x3f0e3ec4,0xbf553f6d,0xbf223f80,0xbf460000,0x3dc93f35,0xbf7f3f35,
0x3f62be48,0xbef13f7b,0x3f75bf55,0x3e953f0e,0x3e95bf6d,0x3f75bec4,0xbef1bec4,0x3f62bf6d,0xbf7f3f0e,0x3dc9bf55,0xbf463f7b,0xbf22be48,
0xbf353f80,0xbf350000,0xbf353f80,0xbf350000,0x3f350000,0xbf353f80,0x3f350000,0xbf353f80,0x3f35bf80,0x3f350000,0x3f35bf80,0x3f350000,
0xbf350000,0x3f35bf80,0xbf350000,0x3f35bf80,0xbf463f80,0xbf220000,0xbf7f3f35,0x3dc9bf35,0x3ef13e48,0xbf623f7b,0xbe953f55,0xbf753f0e,
0x3f75bf6d,0x3e953ec4,0x3f62bec4,0xbef13f6d,0xbdc9bf0e,0x3f7fbf55,0x3f22bf7b,0x3f46be48,0xbf553f80,0xbf0e0000,0xbf0e0000,0x3f55bf80,
0x3e483ec4,0xbf7b3f6d,0xbf7b3f6d,0xbe48bec4,0x3f7bbf35,0xbe483f35,0xbe483f35,0xbf7b3f35,0x3f0ebf6d,0x3f55bec4,0x3f55bec4,0xbf0e3f6d,
0xbf623f80,0xbef10000,0x3e95bf35,0x3f75bf35,0xbdc93f0e,0xbf7f3f55,0xbf223e48,0x3f46bf7b,0x3f46bec4,0xbf223f6d,0xbf7f3f6d,0xbdc9bec4,
0x3f75bf7b,0x3e953e48,0xbef13f55,0xbf623f0e,0xbf6d3f80,0xbec40000,0x3f6dbf80,0x3ec40000,0xbec43f35,0xbf6d3f35,0x3ec4bf35,0x3f6dbf35,
0x3ec40000,0xbf6d3f80,0xbec40000,0x3f6dbf80,0x3f6dbf35,0xbec43f35,0xbf6d3f35,0x3ec4bf35,0xbf753f80,0xbe950000,0x3f62bf35,0xbef13f35,
0xbf223f55,0xbf463f0e,0x3f7fbf7b,0x3dc93e48,0xbdc93ec4,0xbf7f3f6d,0x3f46bf6d,0x3f22bec4,0x3ef1be48,0xbf623f7b,0x3e95bf0e,0x3f75bf55,
0xbf7b3f80,0xbe480000,0x3e480000,0xbf7b3f80,0xbf553f6d,0xbf0e3ec4,0x3f0ebec4,0xbf553f6d,0xbf0e3f35,0xbf553f35,0x3f55bf35,0xbf0e3f35,
0xbe483ec4,0xbf7b3f6d,0x3f7bbf6d,0xbe483ec4,0xbf7f3f80,0xbdc90000,0xbf223f35,0xbf463f35,0xbf753f7b,0xbe953e48,0xbef13f0e,0xbf623f55,
0xbf623f6d,0xbef13ec4,0xbe953ec4,0xbf753f6d,0xbf463f55,0xbf223f0e,0xbdc93e48,0xbf7f3f7b,0x3f803f80,0xbf803f80,0x3f803f80,0xbf803f80,
0x3f803f80,0xbf803f80,0x3f803f80,0xbf803f80,0x3f803f80,0xbf803f80,0x3f803f80,0xbf803f80,0x3f803f80,0xbf803f80,0x3f803f80,0xbf803f80,
0xbdc90000,0xbf7fbf80,0xbf46bf35,0xbf22bf35,0xbe95be48,0xbf75bf7b,0xbf62bf55,0xbef1bf0e,0xbef1bec4,0xbf62bf6d,0xbf75bf6d,0xbe95bec4,
0xbf22bf0e,0xbf46bf55,0xbf7fbf7b,0xbdc9be48,0xbf7bbf80,0x3e480000,0x3e480000,0x3f7b3f80,0xbf55bf6d,0x3f0e3ec4,0x3f0e3ec4,0x3f553f6d,
0xbf0ebf35,0x3f553f35,0x3f553f35,0x3f0e3f35,0xbe48bec4,0x3f7b3f6d,0x3f7b3f6d,0x3e483ec4,0x3e950000,0x3f753f80,0x3ef13f35,0xbf62bf35,
0x3f463f0e,0x3f223f55,0xbdc93e48,0xbf7fbf7b,0x3f7f3f6d,0x3dc93ec4,0xbf22bec4,0xbf46bf6d,0x3f623f7b,0xbef1be48,0xbf75bf55,0xbe95bf0e,
0x3f6d3f80,0xbec40000,0xbf6dbf80,0x3ec40000,0x3ec43f35,0xbf6dbf35,0xbec4bf35,0x3f6d3f35,0xbec40000,0xbf6dbf80,0x3ec40000,0x3f6d3f80,
0xbf6dbf35,0xbec4bf35,0x3f6d3f35,0x3ec43f35,0xbef10000,0xbf62bf80,0x3f753f35,0x3e953f35,0xbf7fbf55,0xbdc9bf0e,0x3f463f7b,0xbf22be48,
0xbf22bf6d,0x3f463ec4,0xbdc93ec4,0xbf7fbf6d,0x3e95be48,0x3f753f7b,0xbf62bf0e,0xbef1bf55,0xbf55bf80,0x3f0e0000,0xbf0e0000,0xbf55bf80,
0x3e48bec4,0x3f7b3f6d,0xbf7bbf6d,0x3e48bec4,0x3f7b3f35,0x3e483f35,0xbe48bf35,0x3f7b3f35,0x3f0e3f6d,0xbf55bec4,0x3f553ec4,0x3f0e3f6d,
0x3f220000,0x3f463f80,0xbdc9bf35,0x3f7f3f35,0x3f623f7b,0xbef13e48,0x3f753f0e,0x3e953f55,0xbe953ec4,0xbf75bf6d,0x3ef13f6d,0xbf62bec4,
0xbf7fbf55,0x3dc9bf0e,0xbf46be48,0xbf22bf7b,0x3f353f80,0xbf350000,0x3f353f80,0xbf350000,0xbf350000,0xbf35bf80,0xbf350000,0xbf35bf80,
0xbf35bf80,0x3f350000,0xbf35bf80,0x3f350000,0x3f350000,0x3f353f80,0x3f350000,0x3f353f80,0xbf460000,0xbf22bf80,0xbf7fbf35,0x3dc9bf35,
0xbef1bf7b,0x3f623e48,0x3e95bf0e,0x3f753f55,0x3f753ec4,0x3e953f6d,0x3f623f6d,0xbef13ec4,0x3dc93f55,0xbf7fbf0e,0xbf223e48,0xbf46bf7b,
0xbf0ebf80,0x3f550000,0x3f550000,0x3f0e3f80,0x3f7b3ec4,0x3e483f6d,0x3e483f6d,0xbf7bbec4,0xbe483f35,0xbf7bbf35,0xbf7bbf35,0x3e48bf35,
0xbf55bf6d,0x3f0ebec4,0x3f0ebec4,0x3f553f6d,0x3f620000,0x3ef13f80,0xbe953f35,0xbf75bf35,0xbdc93f55,0xbf7fbf0e,0xbf22bf7b,0x3f46be48,
0xbf46bf6d,0x3f22bec4,0x3f7f3ec4,0x3dc93f6d,0x3f753e48,0x3e953f7b,0xbef13f0e,0xbf62bf55,0x3ec43f80,0xbf6d0000,0xbec4bf80,0x3f6d0000,
0xbf6dbf35,0x3ec4bf35,0x3f6d3f35,0xbec43f35,0x3f6d0000,0x3ec43f80,0xbf6d0000,0xbec4bf80,0xbec43f35,0xbf6dbf35,0x3ec4bf35,0x3f6d3f35,
0xbf750000,0xbe95bf80,0x3f623f35,0xbef13f35,0x3f22bf0e,0x3f463f55,0xbf7fbe48,0xbdc9bf7b,0xbdc93f6d,0xbf7fbec4,0x3f46bec4,0x3f223f6d,
0xbef1bf7b,0x3f62be48,0xbe953f55,0xbf75bf0e,0xbe48bf80,0x3f7b0000,0xbf7b0000,0xbe48bf80,0x3f0e3f6d,0xbf553ec4,0x3f55bec4,0x3f0e3f6d,
0xbf55bf35,0x3f0ebf35,0xbf0e3f35,0xbf55bf35,0x3f7b3ec4,0xbe483f6d,0x3e48bf6d,0x3f7b3ec4,0x3f7f0000,0x3dc93f80,0x3f22bf35,0x3f463f35,
0xbf753e48,0xbe95bf7b,0xbef13f55,0xbf62bf0e,0x3f62bec4,0x3ef13f6d,0x3e95bf6d,0x3f753ec4,0xbf463f0e,0xbf22bf55,0xbdc93f7b,0xbf7fbe48,
0x3f80,0xbf800000,0x3f80,0xbf800000,0xbf80,0x3f800000,0xbf80,0x3f800000,0x3f80,0xbf800000,0x3f80,0xbf800000,
0xbf80,0x3f800000,0xbf80,0x3f800000,0xbf7f0000,0x3dc9bf80,0xbf22bf35,0x3f46bf35,0x3f753e48,0xbe953f7b,0x3ef13f55,0xbf623f0e,
0xbf62bec4,0x3ef1bf6d,0xbe95bf6d,0x3f75bec4,0x3f463f0e,0xbf223f55,0x3dc93f7b,0xbf7f3e48,0x3e48bf80,0x3f7b0000,0x3f7b0000,0xbe483f80,
0xbf0e3f6d,0xbf55bec4,0xbf55bec4,0x3f0ebf6d,0x3f55bf35,0x3f0e3f35,0x3f0e3f35,0xbf553f35,0xbf7b3ec4,0xbe48bf6d,0xbe48bf6d,0x3f7bbec4,
0x3f750000,0xbe953f80,0xbf623f35,0xbef1bf35,0xbf22bf0e,0x3f46bf55,0x3f7fbe48,0xbdc93f7b,0x3dc93f6d,0xbf7f3ec4,0xbf46bec4,0x3f22bf6d,
0x3ef1bf7b,0x3f623e48,0x3e953f55,0xbf753f0e,0xbec43f80,0xbf6d0000,0x3ec4bf80,0x3f6d0000,0x3f6dbf35,0x3ec43f35,0xbf6d3f35,0xbec4bf35,
0xbf6d0000,0x3ec4bf80,0x3f6d0000,0xbec43f80,0x3ec43f35,0xbf6d3f35,0xbec4bf35,0x3f6dbf35,0xbf620000,0x3ef1bf80,0x3e953f35,0xbf753f35,
0x3dc93f55,0xbf7f3f0e,0x3f22bf7b,0x3f463e48,0x3f46bf6d,0x3f223ec4,0xbf7f3ec4,0x3dc9bf6d,0xbf753e48,0x3e95bf7b,0x3ef13f0e,0xbf623f55,
0x3f0ebf80,0x3f550000,0xbf550000,0x3f0ebf80,0xbf7b3ec4,0x3e48bf6d,0xbe483f6d,0xbf7b3ec4,0x3e483f35,0xbf7b3f35,0x3f7bbf35,0x3e483f35,
0x3f55bf6d,0x3f0e3ec4,0xbf0ebec4,0x3f55bf6d,0x3f460000,0xbf223f80,0x3f7fbf35,0x3dc93f35,0x3ef1bf7b,0x3f62be48,0xbe95bf0e,0x3f75bf55,
0xbf753ec4,0x3e95bf6d,0xbf623f6d,0xbef1bec4,0xbdc93f55,0xbf7f3f0e,0x3f223e48,0xbf463f7b,0xbf353f80,0xbf350000,0xbf353f80,0xbf350000,
0x3f350000,0xbf353f80,0x3f350000,0xbf353f80,0x3f35bf80,0x3f350000,0x3f35bf80,0x3f350000,0xbf350000,0x3f35bf80,0xbf350000,0x3f35bf80,
0xbf220000,0x3f46bf80,0x3dc9bf35,0x3f7fbf35,0xbf623f7b,0xbef1be48,0xbf753f0e,0x3e95bf55,0x3e953ec4,0xbf753f6d,0xbef13f6d,0xbf623ec4,
0x3f7fbf55,0x3dc93f0e,0x3f46be48,0xbf223f7b,0x3f55bf80,0x3f0e0000,0x3f0e0000,0xbf553f80,0xbe48bec4,0x3f7bbf6d,0x3f7bbf6d,0x3e483ec4,
0xbf7b3f35,0x3e48bf35,0x3e48bf35,0x3f7bbf35,0xbf0e3f6d,0xbf553ec4,0xbf553ec4,0x3f0ebf6d,0x3ef10000,0xbf623f80,0xbf753f35,0x3e95bf35,
0x3f7fbf55,0xbdc93f0e,0xbf463f7b,0xbf223e48,0x3f22bf6d,0x3f46bec4,0x3dc93ec4,0xbf7f3f6d,0xbe95be48,0x3f75bf7b,0x3f62bf0e,0xbef13f55,
0xbf6d3f80,0xbec40000,0x3f6dbf80,0x3ec40000,0xbec43f35,0xbf6d3f35,0x3ec4bf35,0x3f6dbf35,0x3ec40000,0xbf6d3f80,0xbec40000,0x3f6dbf80,
0x3f6dbf35,0xbec43f35,0xbf6d3f35,0x3ec4bf35,0xbe950000,0x3f75bf80,0xbef13f35,0xbf623f35,0xbf463f0e,0x3f22bf55,0x3dc93e48,0xbf7f3f7b,
0xbf7f3f6d,0x3dc9bec4,0x3f22bec4,0xbf463f6d,0xbf623f7b,0xbef13e48,0x3f75bf55,0xbe953f0e,0x3f7bbf80,0x3e480000,0xbe480000,0x3f7bbf80,
0x3f55bf6d,0x3f0ebec4,0xbf0e3ec4,0x3f55bf6d,0x3f0ebf35,0x3f55bf35,0xbf553f35,0x3f0ebf35,0x3e48bec4,0x3f7bbf6d,0xbf7b3f6d,0x3e48bec4,
0x3dc90000,0xbf7f3f80,0x3f46bf35,0xbf223f35,0x3e95be48,0xbf753f7b,0x3f62bf55,0xbef13f0e,0x3ef1bec4,0xbf623f6d,0x3f75bf6d,0xbe953ec4,
0x3f22bf0e,0xbf463f55,0x3f7fbf7b,0xbdc93e48,0x3f803f80,0xbf803f80,0x3f803f80,0xbf803f80,0x3f803f80,0xbf803f80,0x3f803f80,0xbf803f80,
0x3f803f80,0xbf803f80,0x3f803f80,0xbf803f80,0x3f803f80,0xbf803f80,0x3f803f80,0xbf803f80,0xbf7fbf80,0x3dc90000,0xbf22bf35,0x3f463f35,
0xbf75bf7b,0x3e953e48,0xbef1bf0e,0x3f623f55,0xbf62bf6d,0x3ef13ec4,0xbe95bec4,0x3f753f6d,0xbf46bf55,0x3f223f0e,0xbdc9be48,0x3f7f3f7b,
0x3f7b3f80,0xbe480000,0xbe480000,0xbf7bbf80,0x3f553f6d,0xbf0ebec4,0xbf0ebec4,0xbf55bf6d,0x3f0e3f35,0xbf55bf35,0xbf55bf35,0xbf0ebf35,
0x3e483ec4,0xbf7bbf6d,0xbf7bbf6d,0xbe48bec4,0xbf75bf80,0x3e950000,0x3f623f35,0x3ef13f35,0xbf22bf55,0x3f463f0e,0x3f7f3f7b,0xbdc93e48,
0xbdc9bec4,0x3f7f3f6d,0x3f463f6d,0xbf22bec4,0x3ef13e48,0x3f623f7b,0x3e953f0e,0xbf75bf55,0x3f6d3f80,0xbec40000,0xbf6dbf80,0x3ec40000,
0x3ec43f35,0xbf6dbf35,0xbec4bf35,0x3f6d3f35,0xbec40000,0xbf6dbf80,0x3ec40000,0x3f6d3f80,0xbf6dbf35,0xbec4bf35,0x3f6d3f35,0x3ec43f35,
0xbf62bf80,0x3ef10000,0x3e953f35,0xbf75bf35,0xbdc9bf0e,0x3f7f3f55,0xbf22be48,0xbf46bf7b,0x3f463ec4,0x3f223f6d,0xbf7fbf6d,0x3dc9bec4,
0x3f753f7b,0xbe953e48,0xbef1bf55,0x3f623f0e,0x3f553f80,0xbf0e0000,0x3f0e0000,0x3f553f80,0xbe483ec4,0xbf7bbf6d,0x3f7b3f6d,0xbe483ec4,
0xbf7bbf35,0xbe48bf35,0x3e483f35,0xbf7bbf35,0xbf0ebf6d,0x3f553ec4,0xbf55bec4,0xbf0ebf6d,0xbf46bf80,0x3f220000,0xbf7fbf35,0xbdc9bf35,
0x3ef1be48,0x3f623f7b,0xbe95bf55,0x3f753f0e,0x3f753f6d,0xbe953ec4,0x3f623ec4,0x3ef13f6d,0xbdc93f0e,0xbf7fbf55,0x3f223f7b,0xbf46be48,
0x3f353f80,0xbf350000,0x3f353f80,0xbf350000,0xbf350000,0xbf35bf80,0xbf350000,0xbf35bf80,0xbf35bf80,0x3f350000,0xbf35bf80,0x3f350000,
0x3f350000,0x3f353f80,0x3f350000,0x3f353f80,0xbf22bf80,0x3f460000,0x3dc9bf35,0x3f7f3f35,0x3f623e48,0x3ef13f7b,0x3f753f55,0xbe953f0e,
0x3e953f6d,0xbf75bec4,0xbef13ec4,0xbf62bf6d,0xbf7fbf0e,0xbdc9bf55,0xbf46bf7b,0x3f22be48,0x3f0e3f80,0xbf550000,0xbf550000,0xbf0ebf80,
0xbf7bbec4,0xbe48bf6d,0xbe48bf6d,0x3f7b3ec4,0x3e48bf35,0x3f7b3f35,0x3f7b3f35,0xbe483f35,0x3f553f6d,0xbf0e3ec4,0xbf0e3ec4,0xbf55bf6d,
0xbef1bf80,0x3f620000,0x3f753f35,0xbe953f35,0x3f7f3f0e,0xbdc93f55,0xbf463e48,0xbf22bf7b,0xbf223ec4,0xbf46bf6d,0xbdc9bf6d,0x3f7f3ec4,
0xbe95bf7b,0x3f753e48,0x3f623f55,0xbef13f0e,0x3ec43f80,0xbf6d0000,0xbec4bf80,0x3f6d0000,0xbf6dbf35,0x3ec4bf35,0x3f6d3f35,0xbec43f35,
0x3f6d0000,0x3ec43f80,0xbf6d0000,0xbec4bf80,0xbec43f35,0xbf6dbf35,0x3ec4bf35,0x3f6d3f35,0xbe95bf80,0x3f750000,0xbef13f35,0xbf62bf35,
0x3f463f55,0xbf223f0e,0xbdc9bf7b,0x3f7f3e48,0xbf7fbec4,0x3dc9bf6d,0x3f223f6d,0xbf463ec4,0x3f62be48,0x3ef13f7b,0xbf75bf0e,0x3e95bf55,
0x3e483f80,0xbf7b0000,0x3f7b0000,0x3e483f80,0xbf0ebf6d,0x3f55bec4,0xbf553ec4,0xbf0ebf6d,0x3f553f35,0xbf0e3f35,0x3f0ebf35,0x3f553f35,
0xbf7bbec4,0x3e48bf6d,0xbe483f6d,0xbf7bbec4,0xbdc9bf80,0x3f7f0000,0xbf46bf35,0x3f22bf35,0x3e953f7b,0xbf753e48,0x3f623f0e,0xbef13f55,
0xbef1bf6d,0x3f62bec4,0xbf75bec4,0x3e95bf6d,0x3f223f55,0xbf463f0e,0x3f7f3e48,0xbdc93f7b,0x3f80,0xbf800000,0x3f80,0xbf800000,
0xbf80,0x3f800000,0xbf80,0x3f800000,0x3f80,0xbf800000,0x3f80,0xbf800000,0xbf80,0x3f800000,0xbf80,0x3f800000,
0x3dc9bf80,0x3f7f0000,0x3f46bf35,0x3f223f35,0xbe953f7b,0xbf75be48,0xbf623f0e,0xbef1bf55,0x3ef1bf6d,0x3f623ec4,0x3f75bec4,0x3e953f6d,
0xbf223f55,0xbf46bf0e,0xbf7f3e48,0xbdc9bf7b,0xbe483f80,0xbf7b0000,0xbf7b0000,0x3e48bf80,0x3f0ebf6d,0x3f553ec4,0x3f553ec4,0xbf0e3f6d,
0xbf553f35,0xbf0ebf35,0xbf0ebf35,0x3f55bf35,0x3f7bbec4,0x3e483f6d,0x3e483f6d,0xbf7b3ec4,0x3e95bf80,0x3f750000,0x3ef13f35,0xbf623f35,
0xbf463f55,0xbf22bf0e,0x3dc9bf7b,0x3f7fbe48,0x3f7fbec4,0x3dc93f6d,0xbf223f6d,0xbf46bec4,0xbf62be48,0x3ef1bf7b,0x3f75bf0e,0x3e953f55,
0xbec43f80,0xbf6d0000,0x3ec4bf80,0x3f6d0000,0x3f6dbf35,0x3ec43f35,0xbf6d3f35,0xbec4bf35,0xbf6d0000,0x3ec4bf80,0x3f6d0000,0xbec43f80,
0x3ec43f35,0xbf6d3f35,0xbec4bf35,0x3f6dbf35,0x3ef1bf80,0x3f620000,0xbf753f35,0xbe95bf35,0xbf7f3f0e,0xbdc9bf55,0x3f463e48,0xbf223f7b,
0x3f223ec4,0xbf463f6d,0x3dc9bf6d,0x3f7fbec4,0x3e95bf7b,0x3f75be48,0xbf623f55,0xbef1bf0e,0xbf0e3f80,0xbf550000,0x3f550000,0xbf0e3f80,
0x3f7bbec4,0xbe483f6d,0x3e48bf6d,0x3f7bbec4,0xbe48bf35,0x3f7bbf35,0xbf7b3f35,0xbe48bf35,0xbf553f6d,0xbf0ebec4,0x3f0e3ec4,0xbf553f6d,
0x3f22bf80,0x3f460000,0xbdc9bf35,0x3f7fbf35,0xbf623e48,0x3ef1bf7b,0xbf753f55,0xbe95bf0e,0xbe953f6d,0xbf753ec4,0x3ef13ec4,0xbf623f6d,
0x3f7fbf0e,0xbdc93f55,0x3f46bf7b,0x3f223e48,0xbf353f80,0xbf350000,0xbf353f80,0xbf350000,0x3f350000,0xbf353f80,0x3f350000,0xbf353f80,
0x3f35bf80,0x3f350000,0x3f35bf80,0x3f350000,0xbf350000,0x3f35bf80,0xbf350000,0x3f35bf80,0x3f46bf80,0x3f220000,0x3f7fbf35,0xbdc93f35,
0xbef1be48,0x3f62bf7b,0x3e95bf55,0x3f75bf0e,0xbf753f6d,0xbe95bec4,0xbf623ec4,0x3ef1bf6d,0x3dc93f0e,0xbf7f3f55,0xbf223f7b,0xbf463e48,
0xbf553f80,0xbf0e0000,0xbf0e0000,0x3f55bf80,0x3e483ec4,0xbf7b3f6d,0xbf7b3f6d,0xbe48bec4,0x3f7bbf35,0xbe483f35,0xbe483f35,0xbf7b3f35,
0x3f0ebf6d,0x3f55bec4,0x3f55bec4,0xbf0e3f6d,0x3f62bf80,0x3ef10000,0xbe953f35,0xbf753f35,0x3dc9bf0e,0x3f7fbf55,0x3f22be48,0xbf463f7b,
0xbf463ec4,0x3f22bf6d,0x3f7fbf6d,0x3dc93ec4,0xbf753f7b,0xbe95be48,0x3ef1bf55,0x3f62bf0e,0xbf6d3f80,0xbec40000,0x3f6dbf80,0x3ec40000,
0xbec43f35,0xbf6d3f35,0x3ec4bf35,0x3f6dbf35,0x3ec40000,0xbf6d3f80,0xbec40000,0x3f6dbf80,0x3f6dbf35,0xbec43f35,0xbf6d3f35,0x3ec4bf35,
0x3f75bf80,0x3e950000,0xbf623f35,0x3ef1bf35,0x3f22bf55,0x3f46bf0e,0xbf7f3f7b,0xbdc9be48,0x3dc9bec4,0x3f7fbf6d,0xbf463f6d,0xbf223ec4,
0xbef13e48,0x3f62bf7b,0xbe953f0e,0xbf753f55,0xbf7b3f80,0xbe480000,0x3e480000,0xbf7b3f80,0xbf553f6d,0xbf0e3ec4,0x3f0ebec4,0xbf553f6d,
0xbf0e3f35,0xbf553f35,0x3f55bf35,0xbf0e3f35,0xbe483ec4,0xbf7b3f6d,0x3f7bbf6d,0xbe483ec4,0x3f7fbf80,0x3dc90000,0x3f22bf35,0x3f46bf35,
0x3f75bf7b,0x3e95be48,0x3ef1bf0e,0x3f62bf55,0x3f62bf6d,0x3ef1bec4,0x3e95bec4,0x3f75bf6d,0x3f46bf55,0x3f22bf0e,0x3dc9be48,0x3f7fbf7b,
0x3f803f80,0xbf803f80,0x3f803f80,0xbf803f80,0x3f803f80,0xbf803f80,0x3f803f80,0xbf803f80,0x3f803f80,0xbf803f80,0x3f803f80,0xbf803f80,
0x3f803f80,0xbf803f80,0x3f803f80,0xbf803f80,0x3dc90000,0x3f7f3f80,0x3f463f35,0x3f223f35,0x3e953e48,0x3f753f7b,0x3f623f55,0x3ef13f0e,
0x3ef13ec4,0x3f623f6d,0x3f753f6d,0x3e953ec4,0x3f223f0e,0x3f463f55,0x3f7f3f7b,0x3dc93e48,0xbf7bbf80,0x3e480000,0x3e480000,0x3f7b3f80,
0xbf55bf6d,0x3f0e3ec4,0x3f0e3ec4,0x3f553f6d,0xbf0ebf35,0x3f553f35,0x3f553f35,0x3f0e3f35,0xbe48bec4,0x3f7b3f6d,0x3f7b3f6d,0x3e483ec4,
0xbe950000,0xbf75bf80,0xbef1bf35,0x3f623f35,0xbf46bf0e,0xbf22bf55,0x3dc9be48,0x3f7f3f7b,0xbf7fbf6d,0xbdc9bec4,0x3f223ec4,0x3f463f6d,
0xbf62bf7b,0x3ef13e48,0x3f753f55,0x3e953f0e,0x3f6d3f80,0xbec40000,0xbf6dbf80,0x3ec40000,0x3ec43f35,0xbf6dbf35,0xbec4bf35,0x3f6d3f35,
0xbec40000,0xbf6dbf80,0x3ec40000,0x3f6d3f80,0xbf6dbf35,0xbec4bf35,0x3f6d3f35,0x3ec43f35,0x3ef10000,0x3f623f80,0xbf75bf35,0xbe95bf35,
0x3f7f3f55,0x3dc93f0e,0xbf46bf7b,0x3f223e48,0x3f223f6d,0xbf46bec4,0x3dc9bec4,0x3f7f3f6d,0xbe953e48,0xbf75bf7b,0x3f623f0e,0x3ef13f55,
0xbf55bf80,0x3f0e0000,0xbf0e0000,0xbf55bf80,0x3e48bec4,0x3f7b3f6d,0xbf7bbf6d,0x3e48bec4,0x3f7b3f35,0x3e483f35,0xbe48bf35,0x3f7b3f35,
0x3f0e3f6d,0xbf55bec4,0x3f553ec4,0x3f0e3f6d,0xbf220000,0xbf46bf80,0x3dc93f35,0xbf7fbf35,0xbf62bf7b,0x3ef1be48,0xbf75bf0e,0xbe95bf55,
0x3e95bec4,0x3f753f6d,0xbef1bf6d,0x3f623ec4,0x3f7f3f55,0xbdc93f0e,0x3f463e48,0x3f223f7b,0x3f353f80,0xbf350000,0x3f353f80,0xbf350000,
0xbf350000,0xbf35bf80,0xbf350000,0xbf35bf80,0xbf35bf80,0x3f350000,0xbf35bf80,0x3f350000,0x3f350000,0x3f353f80,0x3f350000,0x3f353f80,
0x3f460000,0x3f223f80,0x3f7f3f35,0xbdc93f35,0x3ef13f7b,0xbf62be48,0xbe953f0e,0xbf75bf55,0xbf75bec4,0xbe95bf6d,0xbf62bf6d,0x3ef1bec4,
0xbdc9bf55,0x3f7f3f0e,0x3f22be48,0x3f463f7b,0xbf0ebf80,0x3f550000,0x3f550000,0x3f0e3f80,0x3f7b3ec4,0x3e483f6d,0x3e483f6d,0xbf7bbec4,
0xbe483f35,0xbf7bbf35,0xbf7bbf35,0x3e48bf35,0xbf55bf6d,0x3f0ebec4,0x3f0ebec4,0x3f553f6d,0xbf620000,0xbef1bf80,0x3e95bf35,0x3f753f35,
0x3dc9bf55,0x3f7f3f0e,0x3f223f7b,0xbf463e48,0x3f463f6d,0xbf223ec4,0xbf7fbec4,0xbdc9bf6d,0xbf75be48,0xbe95bf7b,0x3ef1bf0e,0x3f623f55,
0x3ec43f80,0xbf6d0000,0xbec4bf80,0x3f6d0000,0xbf6dbf35,0x3ec4bf35,0x3f6d3f35,0xbec43f35,0x3f6d0000,0x3ec43f80,0xbf6d0000,0xbec4bf80,
0xbec43f35,0xbf6dbf35,0x3ec4bf35,0x3f6d3f35,0x3f750000,0x3e953f80,0xbf62bf35,0x3ef1bf35,0xbf223f0e,0xbf46bf55,0x3f7f3e48,0x3dc93f7b,
0x3dc9bf6d,0x3f7f3ec4,0xbf463ec4,0xbf22bf6d,0x3ef13f7b,0xbf623e48,0x3e95bf55,0x3f753f0e,0xbe48bf80,0x3f7b0000,0xbf7b0000,0xbe48bf80,
0x3f0e3f6d,0xbf553ec4,0x3f55bec4,0x3f0e3f6d,0xbf55bf35,0x3f0ebf35,0xbf0e3f35,0xbf55bf35,0x3f7b3ec4,0xbe483f6d,0x3e48bf6d,0x3f7b3ec4,
0xbf7f0000,0xbdc9bf80,0xbf223f35,0xbf46bf35,0x3f75be48,0x3e953f7b,0x3ef1bf55,0x3f623f0e,0xbf623ec4,0xbef1bf6d,0xbe953f6d,0xbf75bec4,
0x3f46bf0e,0x3f223f55,0x3dc9bf7b,0x3f7f3e48,0x3f80,0xbf800000,0x3f80,0xbf800000,0xbf80,0x3f800000,0xbf80,0x3f800000,
0x3f80,0xbf800000,0x3f80,0xbf800000,0xbf80,0x3f800000,0xbf80,0x3f800000,0x3f7f0000,0xbdc93f80,0x3f223f35,0xbf463f35,
0xbf75be48,0x3e95bf7b,0xbef1bf55,0x3f62bf0e,0x3f623ec4,0xbef13f6d,0x3e953f6d,0xbf753ec4,0xbf46bf0e,0x3f22bf55,0xbdc9bf7b,0x3f7fbe48,
0x3e48bf80,0x3f7b0000,0x3f7b0000,0xbe483f80,0xbf0e3f6d,0xbf55bec4,0xbf55bec4,0x3f0ebf6d,0x3f55bf35,0x3f0e3f35,0x3f0e3f35,0xbf553f35,
0xbf7b3ec4,0xbe48bf6d,0xbe48bf6d,0x3f7bbec4,0xbf750000,0x3e95bf80,0x3f62bf35,0x3ef13f35,0x3f223f0e,0xbf463f55,0xbf7f3e48,0x3dc9bf7b,
0xbdc9bf6d,0x3f7fbec4,0x3f463ec4,0xbf223f6d,0xbef13f7b,0xbf62be48,0xbe95bf55,0x3f75bf0e,0xbec43f80,0xbf6d0000,0x3ec4bf80,0x3f6d0000,
0x3f6dbf35,0x3ec43f35,0xbf6d3f35,0xbec4bf35,0xbf6d0000,0x3ec4bf80,0x3f6d0000,0xbec43f80,0x3ec43f35,0xbf6d3f35,0xbec4bf35,0x3f6dbf35,
0x3f620000,0xbef13f80,0xbe95bf35,0x3f75bf35,0xbdc9bf55,0x3f7fbf0e,0xbf223f7b,0xbf46be48,0xbf463f6d,0xbf22bec4,0x3f7fbec4,0xbdc93f6d,
0x3f75be48,0xbe953f7b,0xbef1bf0e,0x3f62bf55,0x3f0ebf80,0x3f550000,0xbf550000,0x3f0ebf80,0xbf7b3ec4,0x3e48bf6d,0xbe483f6d,0xbf7b3ec4,
0x3e483f35,0xbf7b3f35,0x3f7bbf35,0x3e483f35,0x3f55bf6d,0x3f0e3ec4,0xbf0ebec4,0x3f55bf6d,0xbf460000,0x3f22bf80,0xbf7f3f35,0xbdc9bf35,
0xbef13f7b,0xbf623e48,0x3e953f0e,0xbf753f55,0x3f75bec4,0xbe953f6d,0x3f62bf6d,0x3ef13ec4,0x3dc9bf55,0x3f7fbf0e,0xbf22be48,0x3f46bf7b,
0xbf353f80,0xbf350000,0xbf353f80,0xbf350000,0x3f350000,0xbf353f80,0x3f350000,0xbf353f80,0x3f35bf80,0x3f350000,0x3f35bf80,0x3f350000,
0xbf350000,0x3f35bf80,0xbf350000,0x3f35bf80,0x3f220000,0xbf463f80,0xbdc93f35,0xbf7f3f35,0x3f62bf7b,0x3ef13e48,0x3f75bf0e,0xbe953f55,
0xbe95bec4,0x3f75bf6d,0x3ef1bf6d,0x3f62bec4,0xbf7f3f55,0xbdc9bf0e,0xbf463e48,0x3f22bf7b,0x3f55bf80,0x3f0e0000,0x3f0e0000,0xbf553f80,
0xbe48bec4,0x3f7bbf6d,0x3f7bbf6d,0x3e483ec4,0xbf7b3f35,0x3e48bf35,0x3e48bf35,0x3f7bbf35,0xbf0e3f6d,0xbf553ec4,0xbf553ec4,0x3f0ebf6d,
0xbef10000,0x3f62bf80,0x3f75bf35,0xbe953f35,0xbf7f3f55,0x3dc9bf0e,0x3f46bf7b,0x3f22be48,0xbf223f6d,0xbf463ec4,0xbdc9bec4,0x3f7fbf6d,
0x3e953e48,0xbf753f7b,0xbf623f0e,0x3ef1bf55,0xbf6d3f80,0xbec40000,0x3f6dbf80,0x3ec40000,0xbec43f35,0xbf6d3f35,0x3ec4bf35,0x3f6dbf35,
0x3ec40000,0xbf6d3f80,0xbec40000,0x3f6dbf80,0x3f6dbf35,0xbec43f35,0xbf6d3f35,0x3ec4bf35,0x3e950000,0xbf753f80,0x3ef1bf35,0x3f62bf35,
0x3f46bf0e,0xbf223f55,0xbdc9be48,0x3f7fbf7b,0x3f7fbf6d,0xbdc93ec4,0xbf223ec4,0x3f46bf6d,0x3f62bf7b,0x3ef1be48,0xbf753f55,0x3e95bf0e,
0x3f7bbf80,0x3e480000,0xbe480000,0x3f7bbf80,0x3f55bf6d,0x3f0ebec4,0xbf0e3ec4,0x3f55bf6d,0x3f0ebf35,0x3f55bf35,0xbf553f35,0x3f0ebf35,
0x3e48bec4,0x3f7bbf6d,0xbf7b3f6d,0x3e48bec4,0xbdc90000,0x3f7fbf80,0xbf463f35,0x3f22bf35,0xbe953e48,0x3f75bf7b,0xbf623f55,0x3ef1bf0e,
0xbef13ec4,0x3f62bf6d,0xbf753f6d,0x3e95bec4,0xbf223f0e,0x3f46bf55,0xbf7f3f7b,0x3dc9be48,0x40003f80,0x3fb53f80,0x3f80,0xbfb53f80,
0x40004000,0xbfb50000,0x0,0xbfb5c000,0x40004000,0xbfb5c000,0x0,0x3fb50000,0x40004000,0x3fb50000,0x0,0x3fb54000,
0x3fff3f80,0x3fa23f80,0xbe49bf80,0xbfc6bf80,0x3ff53ffb,0xbfe2bec8,0xbf15bec8,0xbf71bffb,0x3fe23fed,0xbf15bfed,0xbf71bf44,0x3ff53f44,
0x3fc63fd5,0x3fff3f8e,0xbfa2bf8e,0x3e493fd5,0x3ffb3f80,0x3f8e3f80,0xbec83f80,0xbfd53f80,0x3fd53fed,0xbffbbf44,0xbf8ebf44,0xbec8bfed,
0x3f8e3fb5,0x3ec8bfb5,0xbfd5bfb5,0x3ffb3fb5,0x3ec83f44,0x3fd53fed,0xbffbbfed,0xbf8e3f44,0x3ff53f80,0x3f713f80,0xbf15bf80,0xbfe2bf80,
0x3fa23fd5,0xbfffbf8e,0xbfc6bf8e,0x3e49bfd5,0x3e493f44,0x3fa2bf44,0xbfffbfed,0x3fc63fed,0xbf71bec8,0x3f153ffb,0xbfe2bffb,0xbff5bec8,
0x3fed3f80,0x3f443f80,0xbf443f80,0xbfed3f80,0x3f443fb5,0xbfedbfb5,0xbfedbfb5,0x3f44bfb5,0xbf440000,0x3fed0000,0xbfedc000,0x3f444000,
0xbfedbfb5,0xbf443fb5,0xbf44bfb5,0xbfedbfb5,0x3fe23f80,0x3f153f80,0xbf71bf80,0xbff5bf80,0x3e493f8e,0xbfc6bfd5,0xbfffbfd5,0x3fa2bf8e,
0xbfc6bf44,0x3fff3f44,0xbfa2bfed,0xbe493fed,0xbff5bffb,0xbfe23ec8,0x3f15bec8,0xbf71bffb,0x3fd53f80,0x3ec83f80,0xbf8e3f80,0xbffb3f80,
0xbec83f44,0xbf8ebfed,0xbffbbfed,0x3fd5bf44,0xbffbbfb5,0x3fd53fb5,0xbec8bfb5,0xbf8e3fb5,0xbf8ebfed,0xbffbbf44,0x3fd53f44,0x3ec8bfed,
0x3fc63f80,0x3e493f80,0xbfa2bf80,0xbfffbf80,0xbf713ec8,0xbf15bffb,0xbfe2bffb,0x3ff5bec8,0xbff5bfed,0x3f713fed,0x3f15bf44,0xbfe23f44,
0x3e49bf8e,0xbfa2bfd5,0x3fff3fd5,0x3fc6bf8e,0x3f80,0xbfb53f80,0xc0003f80,0xbfb53f80,0xc000,0x3fb50000,0x40000000,0xbfb54000,
0x4000,0x3fb5c000,0xc0000000,0x3fb50000,0xc000,0xbfb50000,0x40000000,0x3fb5c000,0xbe493f80,0xbfc63f80,0xbfffbf80,0xbfa2bf80,
0x3f15bffb,0x3f713ec8,0x3ff53ec8,0xbfe23ffb,0xbf713fed,0x3ff5bfed,0xbfe2bf44,0x3f153f44,0x3fa2bfd5,0xbe49bf8e,0x3fc63f8e,0x3fffbfd5,
0xbec83f80,0xbfd53f80,0xbffb3f80,0xbf8e3f80,0x3f8ebfed,0x3ec83f44,0x3fd53f44,0xbffb3fed,0xbfd53fb5,0x3ffbbfb5,0xbf8ebfb5,0xbec83fb5,
0x3ffbbf44,0x3f8ebfed,0x3ec83fed,0x3fd5bf44,0xbf153f80,0xbfe23f80,0xbff5bf80,0xbf71bf80,0x3fc6bfd5,0xbe493f8e,0x3fa23f8e,0xbfff3fd5,
0xbfff3f44,0x3fc6bf44,0xbe49bfed,0xbfa23fed,0x3fe23ec8,0x3ff5bffb,0xbf713ffb,0x3f153ec8,0xbf443f80,0xbfed3f80,0xbfed3f80,0xbf443f80,
0x3fedbfb5,0xbf443fb5,0x3f443fb5,0xbfed3fb5,0xbfed0000,0x3f440000,0x3f44c000,0xbfed4000,0x3f443fb5,0x3fedbfb5,0xbfed3fb5,0xbf443fb5,
0xbf713f80,0xbff53f80,0xbfe2bf80,0xbf15bf80,0x3fffbf8e,0xbfa23fd5,0x3e493fd5,0xbfc63f8e,0xbfa2bf44,0xbe493f44,0x3fc6bfed,0xbfff3fed,
0xbf153ffb,0x3f71bec8,0xbff53ec8,0xbfe23ffb,0xbf8e3f80,0xbffb3f80,0xbfd53f80,0xbec83f80,0x3ffbbf44,0xbfd53fed,0xbec83fed,0xbf8e3f44,
0xbec8bfb5,0xbf8e3fb5,0x3ffbbfb5,0xbfd53fb5,0xbfd53fed,0xbec83f44,0xbf8ebf44,0xbffb3fed,0xbfa23f80,0xbfff3f80,0xbfc6bf80,0xbe49bf80,
0x3fe2bec8,0xbff53ffb,0xbf713ffb,0xbf153ec8,0x3f15bfed,0xbfe23fed,0x3ff5bf44,0xbf713f44,0xbfff3f8e,0xbfc63fd5,0x3e49bfd5,0xbfa23f8e,
0xc0003f80,0xbfb53f80,0x3f80,0x3fb53f80,0xc0004000,0x3fb50000,0x0,0x3fb5c000,0xc0004000,0x3fb5c000,0x0,0xbfb50000,
0xc0004000,0xbfb50000,0x0,0xbfb54000,0xbfff3f80,0xbfa23f80,0x3e49bf80,0x3fc6bf80,0xbff53ffb,0x3fe2bec8,0x3f15bec8,0x3f71bffb,
0xbfe23fed,0x3f15bfed,0x3f71bf44,0xbff53f44,0xbfc63fd5,0xbfff3f8e,0x3fa2bf8e,0xbe493fd5,0xbffb3f80,0xbf8e3f80,0x3ec83f80,0x3fd53f80,
0xbfd53fed,0x3ffbbf44,0x3f8ebf44,0x3ec8bfed,0xbf8e3fb5,0xbec8bfb5,0x3fd5bfb5,0xbffb3fb5,0xbec83f44,0xbfd53fed,0x3ffbbfed,0x3f8e3f44,
0xbff53f80,0xbf713f80,0x3f15bf80,0x3fe2bf80,0xbfa23fd5,0x3fffbf8e,0x3fc6bf8e,0xbe49bfd5,0xbe493f44,0xbfa2bf44,0x3fffbfed,0xbfc63fed,
0x3f71bec8,0xbf153ffb,0x3fe2bffb,0x3ff5bec8,0xbfed3f80,0xbf443f80,0x3f443f80,0x3fed3f80,0xbf443fb5,0x3fedbfb5,0x3fedbfb5,0xbf44bfb5,
0x3f440000,0xbfed0000,0x3fedc000,0xbf444000,0x3fedbfb5,0x3f443fb5,0x3f44bfb5,0x3fedbfb5,0xbfe23f80,0xbf153f80,0x3f71bf80,0x3ff5bf80,
0xbe493f8e,0x3fc6bfd5,0x3fffbfd5,0xbfa2bf8e,0x3fc6bf44,0xbfff3f44,0x3fa2bfed,0x3e493fed,0x3ff5bffb,0x3fe23ec8,0xbf15bec8,0x3f71bffb,
0xbfd53f80,0xbec83f80,0x3f8e3f80,0x3ffb3f80,0x3ec83f44,0x3f8ebfed,0x3ffbbfed,0xbfd5bf44,0x3ffbbfb5,0xbfd53fb5,0x3ec8bfb5,0x3f8e3fb5,
0x3f8ebfed,0x3ffbbf44,0xbfd53f44,0xbec8bfed,0xbfc63f80,0xbe493f80,0x3fa2bf80,0x3fffbf80,0x3f713ec8,0x3f15bffb,0x3fe2bffb,0xbff5bec8,
0x3ff5bfed,0xbf713fed,0xbf15bf44,0x3fe23f44,0xbe49bf8e,0x3fa2bfd5,0xbfff3fd5,0xbfc6bf8e,0x3f80,0x3fb53f80,0x40003f80,0x3fb53f80,
0xc000,0xbfb50000,0xc0000000,0x3fb54000,0x4000,0xbfb5c000,0x40000000,0xbfb50000,0xc000,0x3fb50000,0xc0000000,0xbfb5c000,
0x3e493f80,0x3fc63f80,0x3fffbf80,0x3fa2bf80,0xbf15bffb,0xbf713ec8,0xbff53ec8,0x3fe23ffb,0x3f713fed,0xbff5bfed,0x3fe2bf44,0xbf153f44,
0xbfa2bfd5,0x3e49bf8e,0xbfc63f8e,0xbfffbfd5,0x3ec83f80,0x3fd53f80,0x3ffb3f80,0x3f8e3f80,0xbf8ebfed,0xbec83f44,0xbfd53f44,0x3ffb3fed,
0x3fd53fb5,0xbffbbfb5,0x3f8ebfb5,0x3ec83fb5,0xbffbbf44,0xbf8ebfed,0xbec83fed,0xbfd5bf44,0x3f153f80,0x3fe23f80,0x3ff5bf80,0x3f71bf80,
0xbfc6bfd5,0x3e493f8e,0xbfa23f8e,0x3fff3fd5,0x3fff3f44,0xbfc6bf44,0x3e49bfed,0x3fa23fed,0xbfe23ec8,0xbff5bffb,0x3f713ffb,0xbf153ec8,
0x3f443f80,0x3fed3f80,0x3fed3f80,0x3f443f80,0xbfedbfb5,0x3f443fb5,0xbf443fb5,0x3fed3fb5,0x3fed0000,0xbf440000,0xbf44c000,0x3fed4000,
0xbf443fb5,0xbfedbfb5,0x3fed3fb5,0x3f443fb5,0x3f713f80,0x3ff53f80,0x3fe2bf80,0x3f15bf80,0xbfffbf8e,0x3fa23fd5,0xbe493fd5,0x3fc63f8e,
0x3fa2bf44,0x3e493f44,0xbfc6bfed,0x3fff3fed,0x3f153ffb,0xbf71bec8,0x3ff53ec8,0x3fe23ffb,0x3f8e3f80,0x3ffb3f80,0x3fd53f80,0x3ec83f80,
0xbffbbf44,0x3fd53fed,0x3ec83fed,0x3f8e3f44,0x3ec8bfb5,0x3f8e3fb5,0xbffbbfb5,0x3fd53fb5,0x3fd53fed,0x3ec83f44,0x3f8ebf44,0x3ffb3fed,
0x3fa23f80,0x3fff3f80,0x3fc6bf80,0x3e49bf80,0xbfe2bec8,0x3ff53ffb,0x3f713ffb,0x3f153ec8,0xbf15bfed,0x3fe23fed,0xbff5bf44,0x3f713f44,
0x3fff3f8e,0x3fc63fd5,0xbe49bfd5,0x3fa23f8e,0x40004000,0x3fb54000,0x0,0xbfb50000,0x40004000,0xbfb50000,0x0,0xbfb5c000,
0x40004000,0xbfb5c000,0x0,0x3fb50000,0x40004000,0x3fb50000,0x0,0x3fb54000,0x3fa23fb5,0xbe493fb5,0xbfc6bfb5,0xbfffbfb5,
0x3f713f8e,0xbff5bfd5,0xbfe2bfd5,0x3f15bf8e,0x3f153f44,0x3f71bf44,0xbff5bfed,0x3fe23fed,0x3e493ec8,0x3fc63ffb,0xbfffbffb,0xbfa23ec8,
0xbec80000,0xbfd50000,0xbffbc000,0xbf8ec000,0xbf8ebf44,0xbec8bfed,0xbfd5bfed,0x3ffb3f44,0xbfd5bfb5,0x3ffb3fb5,0xbf8ebfb5,0xbec83fb5,
0xbffbbfed,0xbf8e3f44,0xbec8bf44,0xbfd5bfed,0xbfe2bfb5,0xbff5bfb5,0xbf71bfb5,0x3f15bfb5,0xbfffbffb,0x3fc6bec8,0x3e49bec8,0x3fa23ffb,
0xbfc6bfed,0x3e493fed,0x3fa23f44,0xbfffbf44,0xbf15bf8e,0xbfe2bfd5,0x3ff53fd5,0x3f71bf8e,0xbfedc000,0xbf44c000,0x3f440000,0x3fed0000,
0xbf44bfb5,0x3fed3fb5,0x3fed3fb5,0xbf443fb5,0x3f440000,0xbfed0000,0x3fed4000,0xbf44c000,0x3fed3fb5,0x3f44bfb5,0x3f443fb5,0x3fed3fb5,
0xbf15bfb5,0x3f71bfb5,0x3ff53fb5,0x3fe23fb5,0x3fa23ec8,0x3e493ffb,0x3fc63ffb,0xbfffbec8,0x3fff3fed,0xbfa2bfed,0xbe493f44,0x3fc6bf44,
0x3f713fd5,0x3ff53f8e,0xbfe2bf8e,0xbf153fd5,0x3f8e0000,0x3ffb0000,0x3fd54000,0x3ec84000,0x3ffb3fed,0xbfd53f44,0xbec83f44,0xbf8ebfed,
0x3ec83fb5,0x3f8ebfb5,0xbffbbfb5,0x3fd53fb5,0xbfd5bf44,0xbec83fed,0xbf8ebfed,0xbffbbf44,0x3fff3fb5,0x3fc63fb5,0x3e493fb5,0xbfa23fb5,
0x3f153fd5,0xbfe2bf8e,0xbff5bf8e,0x3f71bfd5,0xbfe2bf44,0x3ff53f44,0xbf71bfed,0xbf153fed,0xbfa2bffb,0xbfffbec8,0x3fc63ec8,0x3e49bffb,
0x4000,0xbfb54000,0xc0000000,0xbfb50000,0xc000,0x3fb50000,0x40000000,0xbfb54000,0x4000,0x3fb5c000,0xc0000000,0x3fb50000,
0xc000,0xbfb50000,0x40000000,0x3fb5c000,0xbfc63fb5,0xbfff3fb5,0xbfa2bfb5,0x3e49bfb5,0x3fe2bf8e,0xbf153fd5,0x3f713fd5,0xbff53f8e,
0xbff53f44,0x3fe2bf44,0xbf15bfed,0xbf713fed,0x3fffbec8,0x3fa2bffb,0x3e493ffb,0x3fc6bec8,0xbffb0000,0xbf8e0000,0x3ec8c000,0x3fd5c000,
0x3fd53f44,0xbffb3fed,0xbf8e3fed,0xbec8bf44,0xbf8ebfb5,0xbec83fb5,0x3fd5bfb5,0xbffb3fb5,0x3ec83fed,0x3fd5bf44,0xbffb3f44,0xbf8e3fed,
0xbf71bfb5,0x3f15bfb5,0x3fe2bfb5,0x3ff5bfb5,0xbe493ffb,0xbfa23ec8,0xbfff3ec8,0x3fc6bffb,0x3fa2bfed,0xbfff3fed,0x3fc63f44,0xbe49bf44,
0xbff53f8e,0xbf713fd5,0xbf15bfd5,0xbfe23f8e,0x3f44c000,0x3fedc000,0x3fed0000,0x3f440000,0xbfed3fb5,0x3f44bfb5,0xbf44bfb5,0x3fedbfb5,
0x3fed0000,0xbf440000,0xbf444000,0x3fedc000,0xbf44bfb5,0xbfed3fb5,0x3fedbfb5,0x3f44bfb5,0x3ff5bfb5,0x3fe2bfb5,0x3f153fb5,0xbf713fb5,
0xbfc6bec8,0x3fffbffb,0x3fa2bffb,0x3e493ec8,0xbe493fed,0x3fc6bfed,0xbfff3f44,0x3fa2bf44,0x3fe2bfd5,0x3f15bf8e,0x3f713f8e,0x3ff5bfd5,
0x3fd50000,0x3ec80000,0xbf8e4000,0xbffb4000,0x3ec8bfed,0x3f8ebf44,0x3ffbbf44,0xbfd53fed,0xbffb3fb5,0x3fd5bfb5,0xbec8bfb5,0xbf8e3fb5,
0x3f8e3f44,0x3ffbbfed,0xbfd53fed,0xbec83f44,0x3e493fb5,0xbfa23fb5,0xbfff3fb5,0xbfc63fb5,0x3ff5bfd5,0xbf713f8e,0x3f153f8e,0xbfe23fd5,
0xbf71bf44,0xbf153f44,0x3fe2bfed,0xbff53fed,0xbfc63ffb,0xbe493ec8,0xbfa2bec8,0xbfff3ffb,0xc0004000,0xbfb54000,0x0,0x3fb50000,
0xc0004000,0x3fb50000,0x0,0x3fb5c000,0xc0004000,0x3fb5c000,0x0,0xbfb50000,0xc0004000,0xbfb50000,0x0,0xbfb54000,
0xbfa23fb5,0x3e493fb5,0x3fc6bfb5,0x3fffbfb5,0xbf713f8e,0x3ff5bfd5,0x3fe2bfd5,0xbf15bf8e,0xbf153f44,0xbf71bf44,0x3ff5bfed,0xbfe23fed,
0xbe493ec8,0xbfc63ffb,0x3fffbffb,0x3fa23ec8,0x3ec80000,0x3fd50000,0x3ffbc000,0x3f8ec000,0x3f8ebf44,0x3ec8bfed,0x3fd5bfed,0xbffb3f44,
0x3fd5bfb5,0xbffb3fb5,0x3f8ebfb5,0x3ec83fb5,0x3ffbbfed,0x3f8e3f44,0x3ec8bf44,0x3fd5bfed,0x3fe2bfb5,0x3ff5bfb5,0x3f71bfb5,0xbf15bfb5,
0x3fffbffb,0xbfc6bec8,0xbe49bec8,0xbfa23ffb,0x3fc6bfed,0xbe493fed,0xbfa23f44,0x3fffbf44,0x3f15bf8e,0x3fe2bfd5,0xbff53fd5,0xbf71bf8e,
0x3fedc000,0x3f44c000,0xbf440000,0xbfed0000,0x3f44bfb5,0xbfed3fb5,0xbfed3fb5,0x3f443fb5,0xbf440000,0x3fed0000,0xbfed4000,0x3f44c000,
0xbfed3fb5,0xbf44bfb5,0xbf443fb5,0xbfed3fb5,0x3f15bfb5,0xbf71bfb5,0xbff53fb5,0xbfe23fb5,0xbfa23ec8,0xbe493ffb,0xbfc63ffb,0x3fffbec8,
0xbfff3fed,0x3fa2bfed,0x3e493f44,0xbfc6bf44,0xbf713fd5,0xbff53f8e,0x3fe2bf8e,0x3f153fd5,0xbf8e0000,0xbffb0000,0xbfd54000,0xbec84000,
0xbffb3fed,0x3fd53f44,0x3ec83f44,0x3f8ebfed,0xbec83fb5,0xbf8ebfb5,0x3ffbbfb5,0xbfd53fb5,0x3fd5bf44,0x3ec83fed,0x3f8ebfed,0x3ffbbf44,
0xbfff3fb5,0xbfc63fb5,0xbe493fb5,0x3fa23fb5,0xbf153fd5,0x3fe2bf8e,0x3ff5bf8e,0xbf71bfd5,0x3fe2bf44,0xbff53f44,0x3f71bfed,0x3f153fed,
0x3fa2bffb,0x3fffbec8,0xbfc63ec8,0xbe49bffb,0x4000,0x3fb54000,0x40000000,0x3fb50000,0xc000,0xbfb50000,0xc0000000,0x3fb54000,
0x4000,0xbfb5c000,0x40000000,0xbfb50000,0xc000,0x3fb50000,0xc0000000,0xbfb5c000,0x3fc63fb5,0x3fff3fb5,0x3fa2bfb5,0xbe49bfb5,
0xbfe2bf8e,0x3f153fd5,0xbf713fd5,0x3ff53f8e,0x3ff53f44,0xbfe2bf44,0x3f15bfed,0x3f713fed,0xbfffbec8,0xbfa2bffb,0xbe493ffb,0xbfc6bec8,
0x3ffb0000,0x3f8e0000,0xbec8c000,0xbfd5c000,0xbfd53f44,0x3ffb3fed,0x3f8e3fed,0x3ec8bf44,0x3f8ebfb5,0x3ec83fb5,0xbfd5bfb5,0x3ffb3fb5,
0xbec83fed,0xbfd5bf44,0x3ffb3f44,0x3f8e3fed,0x3f71bfb5,0xbf15bfb5,0xbfe2bfb5,0xbff5bfb5,0x3e493ffb,0x3fa23ec8,0x3fff3ec8,0xbfc6bffb,
0xbfa2bfed,0x3fff3fed,0xbfc63f44,0x3e49bf44,0x3ff53f8e,0x3f713fd5,0x3f15bfd5,0x3fe23f8e,0xbf44c000,0xbfedc000,0xbfed0000,0xbf440000,
0x3fed3fb5,0xbf44bfb5,0x3f44bfb5,0xbfedbfb5,0xbfed0000,0x3f440000,0x3f444000,0xbfedc000,0x3f44bfb5,0x3fed3fb5,0xbfedbfb5,0xbf44bfb5,
0xbff5bfb5,0xbfe2bfb5,0xbf153fb5,0x3f713fb5,0x3fc6bec8,0xbfffbffb,0xbfa2bffb,0xbe493ec8,0x3e493fed,0xbfc6bfed,0x3fff3f44,0xbfa2bf44,
0xbfe2bfd5,0xbf15bf8e,0xbf713f8e,0xbff5bfd5,0xbfd50000,0xbec80000,0x3f8e4000,0x3ffb4000,0xbec8bfed,0xbf8ebf44,0xbffbbf44,0x3fd53fed,
0x3ffb3fb5,0xbfd5bfb5,0x3ec8bfb5,0x3f8e3fb5,0xbf8e3f44,0xbffbbfed,0x3fd53fed,0x3ec83f44,0xbe493fb5,0x3fa23fb5,0x3fff3fb5,0x3fc63fb5,
0xbff5bfd5,0x3f713f8e,0xbf153f8e,0x3fe23fd5,0x3f71bf44,0x3f153f44,0xbfe2bfed,0x3ff53fed,0x3fc63ffb,0x3e493ec8,0x3fa2bec8,0x3fff3ffb,
0x40004000,0x3fb54000,0x0,0xbfb50000,0x40004000,0xbfb50000,0x0,0xbfb5c000,0x40004000,0xbfb5c000,0x0,0x3fb50000,
0x40004000,0x3fb50000,0x0,0x3fb54000,0xbe490000,0xbfc60000,0xbfffc000,0xbfa2c000,0xbf15bec8,0xbf71bffb,0xbff5bffb,0x3fe23ec8,
0xbf71bf44,0x3ff53f44,0xbfe2bfed,0x3f153fed,0xbfa2bf8e,0x3e493fd5,0xbfc6bfd5,0xbfffbf8e,0xbffbc000,0xbf8ec000,0x3ec80000,0x3fd50000,
0xbfd5bfed,0x3ffb3f44,0x3f8e3f44,0x3ec83fed,0xbf8ebfb5,0xbec83fb5,0x3fd53fb5,0xbffbbfb5,0xbec8bf44,0xbfd5bfed,0x3ffb3fed,0x3f8ebf44,
0x3f150000,0x3fe20000,0x3ff54000,0x3f714000,0x3fc63f8e,0xbe493fd5,0x3fa23fd5,0xbfffbf8e,0x3fff3fed,0xbfc6bfed,0x3e493f44,0x3fa2bf44,
0x3fe23ffb,0x3ff53ec8,0xbf71bec8,0x3f153ffb,0x3fed4000,0x3f444000,0xbf440000,0xbfed0000,0x3f443fb5,0xbfedbfb5,0xbfedbfb5,0x3f44bfb5,
0xbf440000,0x3fed0000,0xbfedc000,0x3f444000,0xbfedbfb5,0xbf443fb5,0xbf44bfb5,0xbfedbfb5,0xbf710000,0xbff50000,0xbfe2c000,0xbf15c000,
0xbfffbfd5,0x3fa2bf8e,0xbe49bf8e,0x3fc63fd5,0xbfa2bfed,0xbe493fed,0x3fc63f44,0xbfffbf44,0x3f15bec8,0xbf71bffb,0x3ff53ffb,0x3fe2bec8,
0xbfd5c000,0xbec8c000,0x3f8e0000,0x3ffb0000,0x3ec8bf44,0x3f8e3fed,0x3ffb3fed,0xbfd53f44,0x3ffb3fb5,0xbfd5bfb5,0x3ec83fb5,0x3f8ebfb5,
0x3f8e3fed,0x3ffb3f44,0xbfd5bf44,0xbec83fed,0x3fa20000,0x3fff0000,0x3fc64000,0x3e494000,0x3fe23ffb,0xbff53ec8,0xbf713ec8,0xbf15bffb,
0xbf153f44,0x3fe2bf44,0xbff5bfed,0x3f713fed,0xbfffbfd5,0xbfc63f8e,0x3e49bf8e,0xbfa2bfd5,0x4000,0xbfb54000,0xc0000000,0xbfb50000,
0xc000,0x3fb50000,0x40000000,0xbfb54000,0x4000,0x3fb5c000,0xc0000000,0x3fb50000,0xc000,0xbfb50000,0x40000000,0x3fb5c000,
0xbfff0000,0xbfa20000,0x3e49c000,0x3fc6c000,0x3ff53ec8,0xbfe23ffb,0xbf153ffb,0xbf71bec8,0xbfe2bf44,0x3f153f44,0x3f71bfed,0xbff53fed,
0x3fc63f8e,0x3fffbfd5,0xbfa23fd5,0x3e493f8e,0x3ec8c000,0x3fd5c000,0x3ffb0000,0x3f8e0000,0xbf8e3fed,0xbec8bf44,0xbfd5bf44,0x3ffbbfed,
0x3fd5bfb5,0xbffb3fb5,0x3f8e3fb5,0x3ec8bfb5,0xbffb3f44,0xbf8e3fed,0xbec8bfed,0xbfd53f44,0x3ff50000,0x3f710000,0xbf154000,0xbfe24000,
0xbfa2bf8e,0x3fffbfd5,0x3fc6bfd5,0xbe493f8e,0x3e493fed,0x3fa2bfed,0xbfff3f44,0x3fc6bf44,0x3f71bffb,0xbf15bec8,0x3fe23ec8,0x3ff5bffb,
0xbf444000,0xbfed4000,0xbfed0000,0xbf440000,0x3fedbfb5,0xbf443fb5,0x3f443fb5,0xbfed3fb5,0xbfed0000,0x3f440000,0x3f44c000,0xbfed4000,
0x3f443fb5,0x3fedbfb5,0xbfed3fb5,0xbf443fb5,0xbfe20000,0xbf150000,0x3f71c000,0x3ff5c000,0x3e493fd5,0xbfc63f8e,0xbfff3f8e,0x3fa2bfd5,
0x3fc6bfed,0xbfff3fed,0x3fa23f44,0x3e49bf44,0xbff53ec8,0xbfe23ffb,0x3f15bffb,0xbf713ec8,0x3f8ec000,0x3ffbc000,0x3fd50000,0x3ec80000,
0xbffb3f44,0x3fd5bfed,0x3ec8bfed,0x3f8ebf44,0x3ec83fb5,0x3f8ebfb5,0xbffb3fb5,0x3fd5bfb5,0x3fd5bfed,0x3ec8bf44,0x3f8e3f44,0x3ffbbfed,
0x3fc60000,0x3e490000,0xbfa24000,0xbfff4000,0x3f71bffb,0x3f15bec8,0x3fe2bec8,0xbff53ffb,0xbff53f44,0x3f71bf44,0x3f15bfed,0xbfe23fed,
0xbe493fd5,0x3fa2bf8e,0xbfff3f8e,0xbfc63fd5,0xc0004000,0xbfb54000,0x0,0x3fb50000,0xc0004000,0x3fb50000,0x0,0x3fb5c000,
0xc0004000,0x3fb5c000,0x0,0xbfb50000,0xc0004000,0xbfb50000,0x0,0xbfb54000,0x3e490000,0x3fc60000,0x3fffc000,0x3fa2c000,
0x3f15bec8,0x3f71bffb,0x3ff5bffb,0xbfe23ec8,0x3f71bf44,0xbff53f44,0x3fe2bfed,0xbf153fed,0x3fa2bf8e,0xbe493fd5,0x3fc6bfd5,0x3fffbf8e,
0x3ffbc000,0x3f8ec000,0xbec80000,0xbfd50000,0x3fd5bfed,0xbffb3f44,0xbf8e3f44,0xbec83fed,0x3f8ebfb5,0x3ec83fb5,0xbfd53fb5,0x3ffbbfb5,
0x3ec8bf44,0x3fd5bfed,0xbffb3fed,0xbf8ebf44,0xbf150000,0xbfe20000,0xbff54000,0xbf714000,0xbfc63f8e,0x3e493fd5,0xbfa23fd5,0x3fffbf8e,
0xbfff3fed,0x3fc6bfed,0xbe493f44,0xbfa2bf44,0xbfe23ffb,0xbff53ec8,0x3f71bec8,0xbf153ffb,0xbfed4000,0xbf444000,0x3f440000,0x3fed0000,
0xbf443fb5,0x3fedbfb5,0x3fedbfb5,0xbf44bfb5,0x3f440000,0xbfed0000,0x3fedc000,0xbf444000,0x3fedbfb5,0x3f443fb5,0x3f44bfb5,0x3fedbfb5,
0x3f710000,0x3ff50000,0x3fe2c000,0x3f15c000,0x3fffbfd5,0xbfa2bf8e,0x3e49bf8e,0xbfc63fd5,0x3fa2bfed,0x3e493fed,0xbfc63f44,0x3fffbf44,
0xbf15bec8,0x3f71bffb,0xbff53ffb,0xbfe2bec8,0x3fd5c000,0x3ec8c000,0xbf8e0000,0xbffb0000,0xbec8bf44,0xbf8e3fed,0xbffb3fed,0x3fd53f44,
0xbffb3fb5,0x3fd5bfb5,0xbec83fb5,0xbf8ebfb5,0xbf8e3fed,0xbffb3f44,0x3fd5bf44,0x3ec83fed,0xbfa20000,0xbfff0000,0xbfc64000,0xbe494000,
0xbfe23ffb,0x3ff53ec8,0x3f713ec8,0x3f15bffb,0x3f153f44,0xbfe2bf44,0x3ff5bfed,0xbf713fed,0x3fffbfd5,0x3fc63f8e,0xbe49bf8e,0x3fa2bfd5,
0x4000,0x3fb54000,0x40000000,0x3fb50000,0xc000,0xbfb50000,0xc0000000,0x3fb54000,0x4000,0xbfb5c000,0x40000000,0xbfb50000,
0xc000,0x3fb50000,0xc0000000,0xbfb5c000,0x3fff0000,0x3fa20000,0xbe49c000,0xbfc6c000,0xbff53ec8,0x3fe23ffb,0x3f153ffb,0x3f71bec8,
0x3fe2bf44,0xbf153f44,0xbf71bfed,0x3ff53fed,0xbfc63f8e,0xbfffbfd5,0x3fa23fd5,0xbe493f8e,0xbec8c000,0xbfd5c000,0xbffb0000,0xbf8e0000,
0x3f8e3fed,0x3ec8bf44,0x3fd5bf44,0xbffbbfed,0xbfd5bfb5,0x3ffb3fb5,0xbf8e3fb5,0xbec8bfb5,0x3ffb3f44,0x3f8e3fed,0x3ec8bfed,0x3fd53f44,
0xbff50000,0xbf710000,0x3f154000,0x3fe24000,0x3fa2bf8e,0xbfffbfd5,0xbfc6bfd5,0x3e493f8e,0xbe493fed,0xbfa2bfed,0x3fff3f44,0xbfc6bf44,
0xbf71bffb,0x3f15bec8,0xbfe23ec8,0xbff5bffb,0x3f444000,0x3fed4000,0x3fed0000,0x3f440000,0xbfedbfb5,0x3f443fb5,0xbf443fb5,0x3fed3fb5,
0x3fed0000,0xbf440000,0xbf44c000,0x3fed4000,0xbf443fb5,0xbfedbfb5,0x3fed3fb5,0x3f443fb5,0x3fe20000,0x3f150000,0xbf71c000,0xbff5c000,
0xbe493fd5,0x3fc63f8e,0x3fff3f8e,0xbfa2bfd5,0xbfc6bfed,0x3fff3fed,0xbfa23f44,0xbe49bf44,0x3ff53ec8,0x3fe23ffb,0xbf15bffb,0x3f713ec8,
0xbf8ec000,0xbffbc000,0xbfd50000,0xbec80000,0x3ffb3f44,0xbfd5bfed,0xbec8bfed,0xbf8ebf44,0xbec83fb5,0xbf8ebfb5,0x3ffb3fb5,0xbfd5bfb5,
0xbfd5bfed,0xbec8bf44,0xbf8e3f44,0xbffbbfed,0xbfc60000,0xbe490000,0x3fa24000,0x3fff4000,0xbf71bffb,0xbf15bec8,0xbfe2bec8,0x3ff53ffb,
0x3ff53f44,0xbf71bf44,0xbf15bfed,0x3fe23fed,0x3e493fd5,0xbfa2bf8e,0x3fff3f8e,0x3fc63fd5,0x40004000,0x3fb54000,0x0,0xbfb50000,
0x40004000,0xbfb50000,0x0,0xbfb5c000,0x40004000,0xbfb5c000,0x0,0x3fb50000,0x40004000,0x3fb50000,0x0,0x3fb54000,
0xbfc6bfb5,0xbfffbfb5,0xbfa2bfb5,0x3e49bfb5,0xbfe2bfd5,0x3f15bf8e,0xbf71bf8e,0x3ff53fd5,0xbff5bfed,0x3fe23fed,0xbf15bf44,0xbf713f44,
0xbfffbffb,0xbfa23ec8,0xbe49bec8,0xbfc6bffb,0x3ec80000,0x3fd50000,0x3ffb4000,0x3f8e4000,0x3f8e3f44,0x3ec83fed,0x3fd53fed,0xbffbbf44,
0x3fd53fb5,0xbffbbfb5,0x3f8e3fb5,0x3ec8bfb5,0x3ffb3fed,0x3f8ebf44,0x3ec83f44,0x3fd53fed,0x3f713fb5,0xbf153fb5,0xbfe2bfb5,0xbff5bfb5,
0xbe493ec8,0xbfa2bffb,0xbfffbffb,0x3fc6bec8,0xbfa2bf44,0x3fff3f44,0xbfc6bfed,0x3e493fed,0xbff5bfd5,0xbf713f8e,0xbf15bf8e,0xbfe2bfd5,
0xbfedc000,0xbf44c000,0x3f440000,0x3fed0000,0xbf44bfb5,0x3fed3fb5,0x3fed3fb5,0xbf443fb5,0x3f440000,0xbfed0000,0x3fed4000,0xbf44c000,
0x3fed3fb5,0x3f44bfb5,0x3f443fb5,0x3fed3fb5,0x3ff53fb5,0x3fe23fb5,0x3f153fb5,0xbf713fb5,0x3fc63ffb,0xbfffbec8,0xbfa2bec8,0xbe49bffb,
0xbe493f44,0x3fc6bf44,0xbfffbfed,0x3fa23fed,0xbfe2bf8e,0xbf153fd5,0xbf71bfd5,0xbff5bf8e,0xbf8e0000,0xbffb0000,0xbfd5c000,0xbec8c000,
0xbffbbfed,0x3fd5bf44,0x3ec8bf44,0x3f8e3fed,0xbec8bfb5,0xbf8e3fb5,0x3ffb3fb5,0xbfd5bfb5,0x3fd53f44,0x3ec8bfed,0x3f8e3fed,0x3ffb3f44,
0xbe49bfb5,0x3fa2bfb5,0x3fff3fb5,0x3fc63fb5,0x3ff53f8e,0xbf713fd5,0x3f153fd5,0xbfe2bf8e,0x3f713fed,0x3f15bfed,0xbfe2bf44,0x3ff53f44,
0xbfc6bec8,0xbe493ffb,0xbfa2bffb,0xbfffbec8,0x4000,0xbfb54000,0xc0000000,0xbfb50000,0xc000,0x3fb50000,0x40000000,0xbfb54000,
0x4000,0x3fb5c000,0xc0000000,0x3fb50000,0xc000,0xbfb50000,0x40000000,0x3fb5c000,0xbfa2bfb5,0x3e49bfb5,0x3fc6bfb5,0x3fffbfb5,
0x3f713fd5,0xbff53f8e,0xbfe23f8e,0x3f15bfd5,0xbf15bfed,0xbf713fed,0x3ff5bf44,0xbfe23f44,0x3e493ffb,0x3fc6bec8,0xbfff3ec8,0xbfa23ffb,
0x3ffb0000,0x3f8e0000,0xbec84000,0xbfd54000,0xbfd5bf44,0x3ffbbfed,0x3f8ebfed,0x3ec83f44,0x3f8e3fb5,0x3ec8bfb5,0xbfd53fb5,0x3ffbbfb5,
0xbec8bfed,0xbfd53f44,0x3ffbbf44,0x3f8ebfed,0xbfe23fb5,0xbff53fb5,0xbf71bfb5,0x3f15bfb5,0x3fffbec8,0xbfc63ffb,0xbe493ffb,0xbfa23ec8,
0xbfc6bf44,0x3e493f44,0x3fa2bfed,0xbfff3fed,0x3f153fd5,0x3fe2bf8e,0xbff53f8e,0xbf713fd5,0x3f44c000,0x3fedc000,0x3fed0000,0x3f440000,
0xbfed3fb5,0x3f44bfb5,0xbf44bfb5,0x3fedbfb5,0x3fed0000,0xbf440000,0xbf444000,0x3fedc000,0xbf44bfb5,0xbfed3fb5,0x3fedbfb5,0x3f44bfb5,
0x3f153fb5,0xbf713fb5,0xbff53fb5,0xbfe23fb5,0x3fa2bffb,0x3e493ec8,0x3fc63ec8,0xbfff3ffb,0xbfff3f44,0x3fa2bf44,0x3e49bfed,0xbfc63fed,
0x3f713f8e,0x3ff5bfd5,0xbfe23fd5,0xbf153f8e,0xbfd50000,0xbec80000,0x3f8ec000,0x3ffbc000,0xbec83fed,0xbf8e3f44,0xbffb3f44,0x3fd5bfed,
0x3ffbbfb5,0xbfd53fb5,0x3ec83fb5,0x3f8ebfb5,0xbf8ebf44,0xbffb3fed,0x3fd5bfed,0x3ec8bf44,0x3fffbfb5,0x3fc6bfb5,0x3e493fb5,0xbfa23fb5,
0xbf15bf8e,0x3fe2bfd5,0x3ff5bfd5,0xbf713f8e,0xbfe23fed,0x3ff5bfed,0xbf71bf44,0xbf153f44,0x3fa23ec8,0x3fffbffb,0xbfc63ffb,0xbe493ec8,
0xc0004000,0xbfb54000,0x0,0x3fb50000,0xc0004000,0x3fb50000,0x0,0x3fb5c000,0xc0004000,0x3fb5c000,0x0,0xbfb50000,
0xc0004000,0xbfb50000,0x0,0xbfb54000,0x3fc6bfb5,0x3fffbfb5,0x3fa2bfb5,0xbe49bfb5,0x3fe2bfd5,0xbf15bf8e,0x3f71bf8e,0xbff53fd5,
0x3ff5bfed,0xbfe23fed,0x3f15bf44,0x3f713f44,0x3fffbffb,0x3fa23ec8,0x3e49bec8,0x3fc6bffb,0xbec80000,0xbfd50000,0xbffb4000,0xbf8e4000,
0xbf8e3f44,0xbec83fed,0xbfd53fed,0x3ffbbf44,0xbfd53fb5,0x3ffbbfb5,0xbf8e3fb5,0xbec8bfb5,0xbffb3fed,0xbf8ebf44,0xbec83f44,0xbfd53fed,
0xbf713fb5,0x3f153fb5,0x3fe2bfb5,0x3ff5bfb5,0x3e493ec8,0x3fa2bffb,0x3fffbffb,0xbfc6bec8,0x3fa2bf44,0xbfff3f44,0x3fc6bfed,0xbe493fed,
0x3ff5bfd5,0x3f713f8e,0x3f15bf8e,0x3fe2bfd5,0x3fedc000,0x3f44c000,0xbf440000,0xbfed0000,0x3f44bfb5,0xbfed3fb5,0xbfed3fb5,0x3f443fb5,
0xbf440000,0x3fed0000,0xbfed4000,0x3f44c000,0xbfed3fb5,0xbf44bfb5,0xbf443fb5,0xbfed3fb5,0xbff53fb5,0xbfe23fb5,0xbf153fb5,0x3f713fb5,
0xbfc63ffb,0x3fffbec8,0x3fa2bec8,0x3e49bffb,0x3e493f44,0xbfc6bf44,0x3fffbfed,0xbfa23fed,0x3fe2bf8e,0x3f153fd5,0x3f71bfd5,0x3ff5bf8e,
0x3f8e0000,0x3ffb0000,0x3fd5c000,0x3ec8c000,0x3ffbbfed,0xbfd5bf44,0xbec8bf44,0xbf8e3fed,0x3ec8bfb5,0x3f8e3fb5,0xbffb3fb5,0x3fd5bfb5,
0xbfd53f44,0xbec8bfed,0xbf8e3fed,0xbffb3f44,0x3e49bfb5,0xbfa2bfb5,0xbfff3fb5,0xbfc63fb5,0xbff53f8e,0x3f713fd5,0xbf153fd5,0x3fe2bf8e,
0xbf713fed,0xbf15bfed,0x3fe2bf44,0xbff53f44,0x3fc6bec8,0x3e493ffb,0x3fa2bffb,0x3fffbec8,0x4000,0x3fb54000,0x40000000,0x3fb50000,
0xc000,0xbfb50000,0xc0000000,0x3fb54000,0x4000,0xbfb5c000,0x40000000,0xbfb50000,0xc000,0x3fb50000,0xc0000000,0xbfb5c000,
0x3fa2bfb5,0xbe49bfb5,0xbfc6bfb5,0xbfffbfb5,0xbf713fd5,0x3ff53f8e,0x3fe23f8e,0xbf15bfd5,0x3f15bfed,0x3f713fed,0xbff5bf44,0x3fe23f44,
0xbe493ffb,0xbfc6bec8,0x3fff3ec8,0x3fa23ffb,0xbffb0000,0xbf8e0000,0x3ec84000,0x3fd54000,0x3fd5bf44,0xbffbbfed,0xbf8ebfed,0xbec83f44,
0xbf8e3fb5,0xbec8bfb5,0x3fd53fb5,0xbffbbfb5,0x3ec8bfed,0x3fd53f44,0xbffbbf44,0xbf8ebfed,0x3fe23fb5,0x3ff53fb5,0x3f71bfb5,0xbf15bfb5,
0xbfffbec8,0x3fc63ffb,0x3e493ffb,0x3fa23ec8,0x3fc6bf44,0xbe493f44,0xbfa2bfed,0x3fff3fed,0xbf153fd5,0xbfe2bf8e,0x3ff53f8e,0x3f713fd5,
0xbf44c000,0xbfedc000,0xbfed0000,0xbf440000,0x3fed3fb5,0xbf44bfb5,0x3f44bfb5,0xbfedbfb5,0xbfed0000,0x3f440000,0x3f444000,0xbfedc000,
0x3f44bfb5,0x3fed3fb5,0xbfedbfb5,0xbf44bfb5,0xbf153fb5,0x3f713fb5,0x3ff53fb5,0x3fe23fb5,0xbfa2bffb,0xbe493ec8,0xbfc63ec8,0x3fff3ffb,
0x3fff3f44,0xbfa2bf44,0xbe49bfed,0x3fc63fed,0xbf713f8e,0xbff5bfd5,0x3fe23fd5,0x3f153f8e,0x3fd50000,0x3ec80000,0xbf8ec000,0xbffbc000,
0x3ec83fed,0x3f8e3f44,0x3ffb3f44,0xbfd5bfed,0xbffbbfb5,0x3fd53fb5,0xbec83fb5,0xbf8ebfb5,0x3f8ebf44,0x3ffb3fed,0xbfd5bfed,0xbec8bf44,
0xbfffbfb5,0xbfc6bfb5,0xbe493fb5,0x3fa23fb5,0x3f15bf8e,0xbfe2bfd5,0xbff5bfd5,0x3f713f8e,0x3fe23fed,0xbff5bfed,0x3f71bf44,0x3f153f44,
0xbfa23ec8,0xbfffbffb,0x3fc63ffb,0x3e493ec8,0x80003f80,0x3f800000,0x80003f80,0x3f800000,0x80003f80,0x3f800000,0x80003f80,0x3f800000,
0x80003f80,0x3f800000,0x80003f80,0x3f800000,0x80003f80,0x3f800000,0x80003f80,0x3f800000,0x80003f80,0x3f800000,0x8000bf80,0xbf800000,
0x3f353f35,0x3f35bf35,0xbf35bf35,0xbf353f35,0x3f800000,0xbf80,0xbf800000,0x3f80,0x3f35bf35,0xbf35bf35,0xbf353f35,0x3f353f35,
0x80003f80,0x3f800000,0x80003f80,0x3f800000,0x3f800000,0xbf80,0x3f800000,0xbf80,0x8000bf80,0xbf800000,0x8000bf80,0xbf800000,
0xbf800000,0x3f80,0xbf800000,0x3f80,0x80003f80,0x3f800000,0x8000bf80,0xbf800000,0x3f35bf35,0xbf35bf35,0xbf353f35,0x3f353f35,
0xbf800000,0x3f80,0x3f800000,0xbf80,0x3f353f35,0x3f35bf35,0xbf35bf35,0xbf353f35,0x80003f80,0x3f800000,0x80003f80,0x3f800000,
0x8000bf80,0xbf800000,0x8000bf80,0xbf800000,0x80003f80,0x3f800000,0x80003f80,0x3f800000,0x8000bf80,0xbf800000,0x8000bf80,0xbf800000,
0x80003f80,0x3f800000,0x8000bf80,0xbf800000,0xbf35bf35,0xbf353f35,0x3f353f35,0x3f35bf35,0x3f800000,0xbf80,0xbf800000,0x3f80,
0xbf353f35,0x3f353f35,0x3f35bf35,0xbf35bf35,0x80003f80,0x3f800000,0x80003f80,0x3f800000,0xbf800000,0x3f80,0xbf800000,0x3f80,
0x8000bf80,0xbf800000,0x8000bf80,0xbf800000,0x3f800000,0xbf80,0x3f800000,0xbf80,0x80003f80,0x3f800000,0x8000bf80,0xbf800000,
0xbf353f35,0x3f353f35,0x3f35bf35,0xbf35bf35,0xbf800000,0x3f80,0x3f800000,0xbf80,0xbf35bf35,0xbf353f35,0x3f353f35,0x3f35bf35,
0x3f803f80,0x80008000,0x80008000,0xbf80bf80,0x3f803f80,0x80008000,0x80008000,0xbf80bf80,0x3f803f80,0x80008000,0x80008000,0xbf80bf80,
0x3f803f80,0x80008000,0x80008000,0xbf80bf80,0x3f353f80,0x3f358000,0x3f358000,0xbf35bf80,0xbf350000,0x3f353f80,0x3f353f80,0x3f358000,
0xbf35bf80,0xbf358000,0xbf358000,0x3f353f80,0x3f350000,0xbf35bf80,0xbf35bf80,0xbf358000,0x3f80,0x3f808000,0x3f808000,0x8000bf80,
0xbf80,0xbf808000,0xbf808000,0x80003f80,0x3f80,0x3f808000,0x3f808000,0x8000bf80,0xbf80,0xbf808000,0xbf808000,0x80003f80,
0xbf353f80,0x3f358000,0x3f358000,0x3f35bf80,0x3f350000,0x3f35bf80,0x3f35bf80,0xbf358000,0x3f35bf80,0xbf358000,0xbf358000,0xbf353f80,
0xbf350000,0xbf353f80,0xbf353f80,0x3f358000,0xbf803f80,0x80008000,0x80008000,0x3f80bf80,0xbf803f80,0x80008000,0x80008000,0x3f80bf80,
0xbf803f80,0x80008000,0x80008000,0x3f80bf80,0xbf803f80,0x80008000,0x80008000,0x3f80bf80,0xbf353f80,0xbf358000,0xbf358000,0x3f35bf80,
0x3f350000,0xbf353f80,0xbf353f80,0xbf358000,0x3f35bf80,0x3f358000,0x3f358000,0xbf353f80,0xbf350000,0x3f35bf80,0x3f35bf80,0x3f358000,
0x3f80,0xbf808000,0xbf808000,0x8000bf80,0xbf80,0x3f808000,0x3f808000,0x80003f80,0x3f80,0xbf808000,0xbf808000,0x8000bf80,
0xbf80,0x3f808000,0x3f808000,0x80003f80,0x3f353f80,0xbf358000,0xbf358000,0xbf35bf80,0xbf350000,0xbf35bf80,0xbf35bf80,0x3f358000,
0xbf35bf80,0x3f358000,0x3f358000,0x3f353f80,0x3f350000,0x3f353f80,0x3f353f80,0xbf358000,0x3f800000,0x0,0x3f800000,0x0,
0x3f800000,0x0,0x3f800000,0x0,0x3f800000,0x0,0x3f800000,0x0,0x3f800000,0x0,0x3f800000,0x0,
0x3f800000,0x0,0x3f7fb10f,0xbd48fb30,0x3f7ec46d,0xbdc8bd36,0x3f7d3aac,0xbe164083,0x3f7b14be,0xbe47c5c2,0x3f7853f8,0xbe78cfcc,
0x3f74fa0b,0xbe94a031,0x3f710908,0xbeac7cd4,0x3f800000,0x0,0x3f7ec46d,0xbdc8bd36,0x3f7b14be,0xbe47c5c2,0x3f74fa0b,0xbe94a031,
0x3f6c835e,0xbec3ef15,0x3f61c598,0xbef15aea,0x3f54db31,0xbf0e39da,0x3f45e403,0xbf226799,0x3f800000,0x0,0x3f7d3aac,0xbe164083,
0x3f74fa0b,0xbe94a031,0x3f676bd8,0xbedae880,0x3f54db31,0xbf0e39da,0x3f3daef9,0xbf2beb4a,0x3f226799,0xbf45e403,0x3f039c3d,0xbf5b941a,
0x3f800000,0x0,0x3f7b14be,0xbe47c5c2,0x3f6c835e,0xbec3ef15,0x3f54db31,0xbf0e39da,0x3f3504f3,0xbf3504f3,0x3f0e39da,0xbf54db31,
0x3ec3ef15,0xbf6c835e,0x3e47c5c2,0xbf7b14be,0x3f800000,0x0,0x3f7853f8,0xbe78cfcc,0x3f61c598,0xbef15aea,0x3f3daef9,0xbf2beb4a,
0x3f0e39da,0xbf54db31,0x3eac7cd4,0xbf710908,0x3dc8bd36,0xbf7ec46d,0xbe164083,0xbf7d3aac,0x3f800000,0x0,0x3f74fa0b,0xbe94a031,
0x3f54db31,0xbf0e39da,0x3f226799,0xbf45e403,0x3ec3ef15,0xbf6c835e,0x3dc8bd36,0xbf7ec46d,0xbe47c5c2,0xbf7b14be,0xbef15aea,0xbf61c598,
0x3f800000,0x0,0x3f710908,0xbeac7cd4,0x3f45e403,0xbf226799,0x3f039c3d,0xbf5b941a,0x3e47c5c2,0xbf7b14be,0xbe164083,0xbf7d3aac,
0xbef15aea,0xbf61c598,0xbf3daef9,0xbf2beb4a,0x3f800000,0x0,0x3f800000,0x0,0x3f800000,0x0,0x3f800000,0x0,
0x3f800000,0x0,0x3f800000,0x0,0x3f800000,0x0,0x3f800000,0x0,0x3f6c835e,0xbec3ef15,0x3f676bd8,0xbedae880,
0x3f61c598,0xbef15aea,0x3f5b941a,0xbf039c3d,0x3f54db31,0xbf0e39da,0x3f4d9f02,0xbf187fc0,0x3f45e403,0xbf226799,0x3f3daef9,0xbf2beb4a,
0x3f3504f3,0xbf3504f3,0x3f226799,0xbf45e403,0x3f0e39da,0xbf54db31,0x3ef15aea,0xbf61c598,0x3ec3ef15,0xbf6c835e,0x3e94a031,0xbf74fa0b,
0x3e47c5c2,0xbf7b14be,0x3dc8bd36,0xbf7ec46d,0x3ec3ef15,0xbf6c835e,0x3e78cfcc,0xbf7853f8,0x3dc8bd36,0xbf7ec46d,0xbd48fb30,0xbf7fb10f,
0xbe47c5c2,0xbf7b14be,0xbeac7cd4,0xbf710908,0xbef15aea,0xbf61c598,0xbf187fc0,0xbf4d9f02,0x0,0xbf800000,0xbe47c5c2,0xbf7b14be,
0xbec3ef15,0xbf6c835e,0xbf0e39da,0xbf54db31,0xbf3504f3,0xbf3504f3,0xbf54db31,0xbf0e39da,0xbf6c835e,0xbec3ef15,0xbf7b14be,0xbe47c5c2,
0xbec3ef15,0xbf6c835e,0xbf187fc0,0xbf4d9f02,0xbf45e403,0xbf226799,0xbf676bd8,0xbedae880,0xbf7b14be,0xbe47c5c2,0xbf7fb10f,0x3d48fb30,
0xbf74fa0b,0x3e94a031,0xbf5b941a,0x3f039c3d,0xbf3504f3,0xbf3504f3,0xbf61c598,0xbef15aea,0xbf7b14be,0xbe47c5c2,0xbf7ec46d,0x3dc8bd36,
0xbf6c835e,0x3ec3ef15,0xbf45e403,0x3f226799,0xbf0e39da,0x3f54db31,0xbe94a031,0x3f74fa0b,0xbf6c835e,0xbec3ef15,0xbf7fb10f,0xbd48fb30,
0xbf74fa0b,0x3e94a031,0xbf4d9f02,0x3f187fc0,0xbf0e39da,0x3f54db31,0xbe78cfcc,0x3f7853f8,0x3dc8bd36,0x3f7ec46d,0x3edae880,0x3f676bd8,
0x80003f80,0x3f800000,0x3f800000,0xbf80,0x3ec43f6d,0x3f6dbec4,0x3f6dbec4,0xbec4bf6d,0x3f353f35,0x3f35bf35,0x3f35bf35,0xbf35bf35,
0x3f6d3ec4,0x3ec4bf6d,0x3ec4bf6d,0xbf6dbec4,0x80003f80,0x3f800000,0xbf800000,0x3f80,0x3f6d3ec4,0x3ec4bf6d,0xbec43f6d,0x3f6d3ec4,
0x3f35bf35,0xbf35bf35,0x3f353f35,0x3f35bf35,0xbec4bf6d,0xbf6d3ec4,0x3f6dbec4,0xbec4bf6d,0x80003f80,0x3f800000,0x3f800000,0xbf80,
0x3f6dbec4,0xbec4bf6d,0xbec4bf6d,0xbf6d3ec4,0xbf35bf35,0xbf353f35,0xbf353f35,0x3f353f35,0xbec43f6d,0x3f6d3ec4,0x3f6d3ec4,0x3ec4bf6d,
0x80003f80,0x3f800000,0xbf800000,0x3f80,0x3ec4bf6d,0xbf6dbec4,0x3f6d3ec4,0x3ec4bf6d,0xbf353f35,0x3f353f35,0xbf35bf35,0xbf353f35,
0x3f6dbec4,0xbec4bf6d,0x3ec43f6d,0x3f6dbec4,0x80003f80,0x3f800000,0x3f800000,0xbf80,0xbec4bf6d,0xbf6d3ec4,0xbf6d3ec4,0x3ec43f6d,
0x3f353f35,0x3f35bf35,0x3f35bf35,0xbf35bf35,0xbf6dbec4,0xbec43f6d,0xbec43f6d,0x3f6d3ec4,0x80003f80,0x3f800000,0xbf800000,0x3f80,
0xbf6dbec4,0xbec43f6d,0x3ec4bf6d,0xbf6dbec4,0x3f35bf35,0xbf35bf35,0x3f353f35,0x3f35bf35,0x3ec43f6d,0x3f6dbec4,0xbf6d3ec4,0x3ec43f6d,
0x80003f80,0x3f800000,0x3f800000,0xbf80,0xbf6d3ec4,0x3ec43f6d,0x3ec43f6d,0x3f6dbec4,0xbf35bf35,0xbf353f35,0xbf353f35,0x3f353f35,
0x3ec4bf6d,0xbf6dbec4,0xbf6dbec4,0xbec43f6d,0x80003f80,0x3f800000,0xbf800000,0x3f80,0xbec43f6d,0x3f6d3ec4,0xbf6dbec4,0xbec43f6d,
0xbf353f35,0x3f353f35,0xbf35bf35,0xbf353f35,0xbf6d3ec4,0x3ec43f6d,0xbec4bf6d,0xbf6d3ec4,0x3f803f80,0x80008000,0x80008000,0xbf80bf80,
0x3f803f80,0x80008000,0x80008000,0xbf80bf80,0x3f803f80,0x80008000,0x80008000,0xbf80bf80,0x3f803f80,0x80008000,0x80008000,0xbf80bf80,
0x3ec43f6d,0x3f6d3ec4,0x3f6d3ec4,0xbec4bf6d,0xbf6dbec4,0x3ec43f6d,0x3ec43f6d,0x3f6d3ec4,0xbec4bf6d,0xbf6dbec4,0xbf6dbec4,0x3ec43f6d,
0x3f6d3ec4,0xbec4bf6d,0xbec4bf6d,0xbf6dbec4,0xbf353f35,0x3f353f35,0x3f353f35,0x3f35bf35,0x3f35bf35,0xbf35bf35,0xbf35bf35,0xbf353f35,
0xbf353f35,0x3f353f35,0x3f353f35,0x3f35bf35,0x3f35bf35,0xbf35bf35,0xbf35bf35,0xbf353f35,0xbf6d3ec4,0xbec43f6d,0xbec43f6d,0x3f6dbec4,
0xbec43f6d,0x3f6dbec4,0x3f6dbec4,0x3ec4bf6d,0x3f6dbec4,0x3ec4bf6d,0x3ec4bf6d,0xbf6d3ec4,0x3ec4bf6d,0xbf6d3ec4,0xbf6d3ec4,0xbec43f6d,
0x0,0xbf803f80,0xbf803f80,0x80008000,0x0,0xbf803f80,0xbf803f80,0x80008000,0x0,0xbf803f80,0xbf803f80,0x80008000,
0x0,0xbf803f80,0xbf803f80,0x80008000,0x3f6dbec4,0xbec43f6d,0xbec43f6d,0xbf6d3ec4,0x3ec4bf6d,0x3f6dbec4,0x3f6dbec4,0xbec43f6d,
0xbf6d3ec4,0x3ec4bf6d,0x3ec4bf6d,0x3f6dbec4,0xbec43f6d,0xbf6d3ec4,0xbf6d3ec4,0x3ec4bf6d,0x3f35bf35,0x3f353f35,0x3f353f35,0xbf353f35,
0xbf353f35,0xbf35bf35,0xbf35bf35,0x3f35bf35,0x3f35bf35,0x3f353f35,0x3f353f35,0xbf353f35,0xbf353f35,0xbf35bf35,0xbf35bf35,0x3f35bf35,
0xbec4bf6d,0x3f6d3ec4,0x3f6d3ec4,0x3ec43f6d,0x3f6d3ec4,0x3ec43f6d,0x3ec43f6d,0xbf6dbec4,0x3ec43f6d,0xbf6dbec4,0xbf6dbec4,0xbec4bf6d,
0xbf6dbec4,0xbec4bf6d,0xbec4bf6d,0x3f6d3ec4,0x3f800000,0x0,0x3f7fec43,0xbcc90ab0,0x3f7fb10f,0xbd48fb30,0x3f7f4e6d,0xbd96a905,
0x3f7ec46d,0xbdc8bd36,0x3f7e1324,0xbdfab273,0x3f7d3aac,0xbe164083,0x3f7c3b28,0xbe2f10a2,0x3f800000,0x0,0x3f7f4e6d,0xbd96a905,
0x3f7d3aac,0xbe164083,0x3f79c79d,0xbe605c13,0x3f74fa0b,0xbe94a031,0x3f6ed89e,0xbeb8442a,0x3f676bd8,0xbedae880,0x3f5ebe05,0xbefc5d27,
0x3f800000,0x0,0x3f7e1324,0xbdfab273,0x3f7853f8,0xbe78cfcc,0x3f6ed89e,0xbeb8442a,0x3f61c598,0xbef15aea,0x3f514d3d,0xbf13682a,
0x3f3daef9,0xbf2beb4a,0x3f273656,0xbf41d870,0x3f800000,0x0,0x3f7c3b28,0xbe2f10a2,0x3f710908,0xbeac7cd4,0x3f5ebe05,0xbefc5d27,
0x3f45e403,0xbf226799,0x3f273656,0xbf41d870,0x3f039c3d,0xbf5b941a,0x3eb8442a,0xbf6ed89e,0x3f800000,0x0,0x3f79c79d,0xbe605c13,
0x3f676bd8,0xbedae880,0x3f49d112,0xbf1d7fd1,0x3f226799,0xbf45e403,0x3ee63375,0xbf64aa59,0x3e78cfcc,0xbf7853f8,0x3cc90ab0,0xbf7fec43,
0x3f800000,0x0,0x3f76ba07,0xbe888e93,0x3f5b941a,0xbf039c3d,0x3f3085bb,0xbf396842,0x3ef15aea,0xbf61c598,0x3e605c13,0xbf79c79d,
0xbd48fb30,0xbf7fb10f,0xbea09ae5,0xbf731447,0x3f800000,0x0,0x3f731447,0xbea09ae5,0x3f4d9f02,0xbf187fc0,0x3f13682a,0xbf514d3d,
0x3e94a031,0xbf74fa0b,0xbcc90ab0,0xbf7fec43,0xbeac7cd4,0xbf710908,0xbf1d7fd1,0xbf49d112,0x3f800000,0x0,0x3f6ed89e,0xbeb8442a,
0x3f3daef9,0xbf2beb4a,0x3ee63375,0xbf64aa59,0x3dc8bd36,0xbf7ec46d,0xbe888e93,0xbf76ba07,0xbf187fc0,0xbf4d9f02,0xbf584853,0xbf08f59b,
0x3f7b14be,0xbe47c5c2,0x3f79c79d,0xbe605c13,0x3f7853f8,0xbe78cfcc,0x3f76ba07,0xbe888e93,0x3f74fa0b,0xbe94a031,0x3f731447,0xbea09ae5,
0x3f710908,0xbeac7cd4,0x3f6ed89e,0xbeb8442a,0x3f54db31,0xbf0e39da,0x3f49d112,0xbf1d7fd1,0x3f3daef9,0xbf2beb4a,0x3f3085bb,0xbf396842,
0x3f226799,0xbf45e403,0x3f13682a,0xbf514d3d,0x3f039c3d,0xbf5b941a,0x3ee63375,0xbf64aa59,0x3f0e39da,0xbf54db31,0x3ee63375,0xbf64aa59,
0x3eac7cd4,0xbf710908,0x3e605c13,0xbf79c79d,0x3dc8bd36,0xbf7ec46d,0xbcc90ab0,0xbf7fec43,0xbe164083,0xbf7d3aac,0xbe888e93,0xbf76ba07,
0x3e47c5c2,0xbf7b14be,0x3cc90ab0,0xbf7fec43,0xbe164083,0xbf7d3aac,0xbea09ae5,0xbf731447,0xbef15aea,0xbf61c598,0xbf1d7fd1,0xbf49d112,
0xbf3daef9,0xbf2beb4a,0xbf584853,0xbf08f59b,0xbe47c5c2,0xbf7b14be,0xbecf7bca,0xbf6a09a7,0xbf187fc0,0xbf4d9f02,0xbf41d870,0xbf273656,
0xbf61c598,0xbef15aea,0xbf76ba07,0xbe888e93,0xbf7fb10f,0xbd48fb30,0xbf7c3b28,0x3e2f10a2,0xbf0e39da,0xbf54db31,0xbf41d870,0xbf273656,
0xbf676bd8,0xbedae880,0xbf7c3b28,0xbe2f10a2,0xbf7ec46d,0x3dc8bd36,0xbf6ed89e,0x3eb8442a,0xbf4d9f02,0x3f187fc0,0xbf1d7fd1,0x3f49d112,
0xbf54db31,0xbf0e39da,0xbf76ba07,0xbe888e93,0xbf7fb10f,0x3d48fb30,0xbf6ed89e,0x3eb8442a,0xbf45e403,0x3f226799,0xbf08f59b,0x3f584853,
0xbe78cfcc,0x3f7853f8,0x3d96a905,0x3f7f4e6d,0xbf7b14be,0xbe47c5c2,0xbf7c3b28,0x3e2f10a2,0xbf5b941a,0x3f039c3d,0xbf1d7fd1,0x3f49d112,
0xbe94a031,0x3f74fa0b,0x3d96a905,0x3f7f4e6d,0x3edae880,0x3f676bd8,0x3f396842,0x3f3085bb,0x80003f80,0x80003f80,0x80003f80,0x80003f80,
0x80003f80,0x80003f80,0x80003f80,0x80003f80,0x80003f80,0x80003f80,0x80003f80,0x80003f80,0x80003f80,0x80003f80,0x80003f80,0x80003f80,
0x3f800000,0x3f800000,0x3f800000,0x3f800000,0x3f800000,0x3f800000,0x3f800000,0x3f800000,0x3f800000,0x3f800000,0x3f800000,0x3f800000,
0x3f800000,0x3f800000,0x3f800000,0x3f800000,0x80003f80,0x3f353f35,0x80003f80,0x3f353f35,0x3f800000,0x3f35bf35,0x3f800000,0x3f35bf35,
0x8000bf80,0xbf35bf35,0x8000bf80,0xbf35bf35,0xbf800000,0xbf353f35,0xbf800000,0xbf353f35,0x3f800000,0x3f35bf35,0x3f800000,0x3f35bf35,
0xbf80,0xbf35bf35,0xbf80,0xbf35bf35,0xbf800000,0xbf353f35,0xbf800000,0xbf353f35,0x3f80,0x3f353f35,0x3f80,0x3f353f35,
0x80003f80,0x3f800000,0x80003f80,0x3f800000,0x8000bf80,0xbf800000,0x8000bf80,0xbf800000,0x80003f80,0x3f800000,0x80003f80,0x3f800000,
0x8000bf80,0xbf800000,0x8000bf80,0xbf800000,0x3f800000,0xbf80,0x3f800000,0xbf80,0xbf800000,0x3f80,0xbf800000,0x3f80,
0x3f800000,0xbf80,0x3f800000,0xbf80,0xbf800000,0x3f80,0xbf800000,0x3f80,0x80003f80,0x3f35bf35,0x80003f80,0x3f35bf35,
0xbf800000,0x3f353f35,0xbf800000,0x3f353f35,0x8000bf80,0xbf353f35,0x8000bf80,0xbf353f35,0x3f800000,0xbf35bf35,0x3f800000,0xbf35bf35,
0x3f800000,0xbf35bf35,0x3f800000,0xbf35bf35,0x3f80,0x3f35bf35,0x3f80,0x3f35bf35,0xbf800000,0x3f353f35,0xbf800000,0x3f353f35,
0xbf80,0xbf353f35,0xbf80,0xbf353f35,0x80003f80,0x3ec43f6d,0x8000bf80,0xbec4bf6d,0x3f353f35,0x3f6d3ec4,0xbf35bf35,0xbf6dbec4,
0x3f800000,0x3f6dbec4,0xbf800000,0xbf6d3ec4,0x3f35bf35,0x3ec4bf6d,0xbf353f35,0xbec43f6d,0x3f800000,0x3f6dbec4,0xbf800000,0xbf6d3ec4,
0x3f35bf35,0x3ec4bf6d,0xbf353f35,0xbec43f6d,0xbf80,0xbec4bf6d,0x3f80,0x3ec43f6d,0xbf35bf35,0xbf6dbec4,0x3f353f35,0x3f6d3ec4,
0x80003f80,0x3f6d3ec4,0x8000bf80,0xbf6dbec4,0x3f35bf35,0xbec4bf6d,0xbf353f35,0x3ec43f6d,0xbf800000,0xbec43f6d,0x3f800000,0x3ec4bf6d,
0x3f353f35,0x3f6dbec4,0xbf35bf35,0xbf6d3ec4,0x3f800000,0x3ec4bf6d,0xbf800000,0xbec43f6d,0xbf35bf35,0xbf6d3ec4,0x3f353f35,0x3f6dbec4,
0x3f80,0x3f6d3ec4,0xbf80,0xbf6dbec4,0x3f35bf35,0xbec4bf6d,0xbf353f35,0x3ec43f6d,0x80003f80,0x3f6dbec4,0x8000bf80,0xbf6d3ec4,
0xbf35bf35,0xbec43f6d,0x3f353f35,0x3ec4bf6d,0x3f800000,0xbec4bf6d,0xbf800000,0x3ec43f6d,0xbf353f35,0x3f6d3ec4,0x3f35bf35,0xbf6dbec4,
0x3f800000,0xbec4bf6d,0xbf800000,0x3ec43f6d,0xbf353f35,0x3f6d3ec4,0x3f35bf35,0xbf6dbec4,0xbf80,0xbf6d3ec4,0x3f80,0x3f6dbec4,
0x3f353f35,0x3ec4bf6d,0xbf35bf35,0xbec43f6d,0x80003f80,0x3ec4bf6d,0x8000bf80,0xbec43f6d,0xbf353f35,0x3f6dbec4,0x3f35bf35,0xbf6d3ec4,
0xbf800000,0x3f6d3ec4,0x3f800000,0xbf6dbec4,0xbf35bf35,0x3ec43f6d,0x3f353f35,0xbec4bf6d,0x3f800000,0xbf6dbec4,0xbf800000,0x3f6d3ec4,
0x3f353f35,0xbec4bf6d,0xbf35bf35,0x3ec43f6d,0x3f80,0x3ec4bf6d,0xbf80,0xbec43f6d,0xbf353f35,0x3f6dbec4,0x3f35bf35,0xbf6d3ec4,
0x80003f80,0x8000bf80,0x80003f80,0x8000bf80,0x80003f80,0x8000bf80,0x80003f80,0x8000bf80,0x80003f80,0x8000bf80,0x80003f80,0x8000bf80,
0x80003f80,0x8000bf80,0x80003f80,0x8000bf80,0x3f800000,0xbf800000,0x3f800000,0xbf800000,0x3f800000,0xbf800000,0x3f800000,0xbf800000,
0x3f800000,0xbf800000,0x3f800000,0xbf800000,0x3f800000,0xbf800000,0x3f800000,0xbf800000,0x80003f80,0xbf35bf35,0x80003f80,0xbf35bf35,
0x3f800000,0xbf353f35,0x3f800000,0xbf353f35,0x8000bf80,0x3f353f35,0x8000bf80,0x3f353f35,0xbf800000,0x3f35bf35,0xbf800000,0x3f35bf35,
0x3f800000,0xbf353f35,0x3f800000,0xbf353f35,0xbf80,0x3f353f35,0xbf80,0x3f353f35,0xbf800000,0x3f35bf35,0xbf800000,0x3f35bf35,
0x3f80,0xbf35bf35,0x3f80,0xbf35bf35,0x80003f80,0xbf800000,0x80003f80,0xbf800000,0x8000bf80,0x3f800000,0x8000bf80,0x3f800000,
0x80003f80,0xbf800000,0x80003f80,0xbf800000,0x8000bf80,0x3f800000,0x8000bf80,0x3f800000,0x3f800000,0x3f80,0x3f800000,0x3f80,
0xbf800000,0xbf80,0xbf800000,0xbf80,0x3f800000,0x3f80,0x3f800000,0x3f80,0xbf800000,0xbf80,0xbf800000,0xbf80,
0x80003f80,0xbf353f35,0x80003f80,0xbf353f35,0xbf800000,0xbf35bf35,0xbf800000,0xbf35bf35,0x8000bf80,0x3f35bf35,0x8000bf80,0x3f35bf35,
0x3f800000,0x3f353f35,0x3f800000,0x3f353f35,0x3f800000,0x3f353f35,0x3f800000,0x3f353f35,0x3f80,0xbf353f35,0x3f80,0xbf353f35,
0xbf800000,0xbf35bf35,0xbf800000,0xbf35bf35,0xbf80,0x3f35bf35,0xbf80,0x3f35bf35,0x80003f80,0xbec4bf6d,0x8000bf80,0x3ec43f6d,
0x3f353f35,0xbf6dbec4,0xbf35bf35,0x3f6d3ec4,0x3f800000,0xbf6d3ec4,0xbf800000,0x3f6dbec4,0x3f35bf35,0xbec43f6d,0xbf353f35,0x3ec4bf6d,
0x3f800000,0xbf6d3ec4,0xbf800000,0x3f6dbec4,0x3f35bf35,0xbec43f6d,0xbf353f35,0x3ec4bf6d,0xbf80,0x3ec43f6d,0x3f80,0xbec4bf6d,
0xbf35bf35,0x3f6d3ec4,0x3f353f35,0xbf6dbec4,0x80003f80,0xbf6dbec4,0x8000bf80,0x3f6d3ec4,0x3f35bf35,0x3ec43f6d,0xbf353f35,0xbec4bf6d,
0xbf800000,0x3ec4bf6d,0x3f800000,0xbec43f6d,0x3f353f35,0xbf6d3ec4,0xbf35bf35,0x3f6dbec4,0x3f800000,0xbec43f6d,0xbf800000,0x3ec4bf6d,
0xbf35bf35,0x3f6dbec4,0x3f353f35,0xbf6d3ec4,0x3f80,0xbf6dbec4,0xbf80,0x3f6d3ec4,0x3f35bf35,0x3ec43f6d,0xbf353f35,0xbec4bf6d,
0x80003f80,0xbf6d3ec4,0x8000bf80,0x3f6dbec4,0xbf35bf35,0x3ec4bf6d,0x3f353f35,0xbec43f6d,0x3f800000,0x3ec43f6d,0xbf800000,0xbec4bf6d,
0xbf353f35,0xbf6dbec4,0x3f35bf35,0x3f6d3ec4,0x3f800000,0x3ec43f6d,0xbf800000,0xbec4bf6d,0xbf353f35,0xbf6dbec4,0x3f35bf35,0x3f6d3ec4,
0xbf80,0x3f6dbec4,0x3f80,0xbf6d3ec4,0x3f353f35,0xbec43f6d,0xbf35bf35,0x3ec4bf6d,0x80003f80,0xbec43f6d,0x8000bf80,0x3ec4bf6d,
0xbf353f35,0xbf6d3ec4,0x3f35bf35,0x3f6dbec4,0xbf800000,0xbf6dbec4,0x3f800000,0x3f6d3ec4,0xbf35bf35,0xbec4bf6d,0x3f353f35,0x3ec43f6d,
0x3f800000,0x3f6d3ec4,0xbf800000,0xbf6dbec4,0x3f353f35,0x3ec43f6d,0xbf35bf35,0xbec4bf6d,0x3f80,0xbec43f6d,0xbf80,0x3ec4bf6d,
0xbf353f35,0xbf6d3ec4,0x3f35bf35,0x3f6dbec4,
};
constexpr int TB_F = 0, TB_E = 512, TB_P2 = 1024;

enum { C_EP = 0, C_Z1 = 32, C_Z2 = 96, C_H3 = 128, C_U = 160, C_TOTAL = 256 };
struct Scratch {
  unsigned cnt[C_TOTAL];
  uint32_t mod[6 * D_ + 384];
  uint32_t z1[120 * 5120];
  uint32_t z2[128 * 4800];
  uint32_t x1[S_ * D_ / 2];
  uint8_t h3[32 * 18 * 4096];
  uint8_t u[72 * D_ * 128];
  uint4 part[128 * 1152];
};
__device__ __align__(1024) Scratch g_s;

#define PF2 8
#define PF2K 16
#define HOLDA 3
#define GOAT 1
#define HOLD1 0
#define XPOS 0
#define HW bulk_commit_wait
#define H3W 0
#define X1K 10
#define PEEK 1
#define H3G 2
#define NG1 2

#define FAILCNT(k) do {} while (0)
#define CK(k) do {} while (0)
#define CKX(k) do {} while (0)
#define TS(k) do {} while (0)
#define TSC(k) do {} while (0)
struct Maps { CUtensorMap w1a, w1b, w2, x1, out, z1, z2, h3[2], wf[4], wm; };
struct Params {
  const __nv_bfloat16 *x, *c, *wmod;
  Scratch* s;
  const uint4* tab;
  const __nv_bfloat16 *wr, *wi, *w1, *w2, *b1, *b2;
};

__device__ __forceinline__ uint32_t smem_u32(const void* p) { return (uint32_t)__cvta_generic_to_shared(p); }
__device__ __forceinline__ void mbar_init(uint32_t b, int c) { asm volatile("mbarrier.init.shared::cta.b64 [%0], %1;" ::"r"(b), "r"(c)); }
__device__ __forceinline__ void mbar_expect(uint32_t b, int bytes) { asm volatile("mbarrier.arrive.expect_tx.shared::cta.b64 _, [%0], %1;" ::"r"(b), "r"(bytes) : "memory"); }
__device__ __forceinline__ void mbar_arrive(uint32_t b) { asm volatile("mbarrier.arrive.shared::cta.b64 _, [%0];" ::"r"(b) : "memory"); }
#define MBAR_WAIT(SEM)                                                                                                         \
  asm volatile("{\n.reg .pred p;\n.reg .u32 it;\nmov.u32 it, 0;\nW:\nmbarrier.try_wait.parity" SEM ".shared::cta.b64 p, [%0], %1;\n" \
               "@p bra.uni D;\nadd.u32 it, it, 1;\nsetp.lt.u32 p, it, 0x400000;\n@p bra.uni W;\ntrap;\nD:\n}" ::"r"(b), "r"(ph) : "memory")
__device__ __forceinline__ void mbar_wait(uint32_t b, int ph) { MBAR_WAIT(""); }
__device__ __forceinline__ uint32_t mbar_test(uint32_t b, int ph) {
  uint32_t ok;
  asm volatile("{\n.reg .pred p;\nmbarrier.test_wait.parity.shared::cta.b64 p, [%1], %2;\nselp.u32 %0, 1, 0, p;\n}\n" : "=r"(ok) : "r"(b), "r"(ph) : "memory");
  return ok;
}
__device__ __forceinline__ void tma2d(uint32_t dst, const CUtensorMap* m, int c0, int c1, uint32_t bar) {
  asm volatile("cp.async.bulk.tensor.2d.shared::cluster.global.mbarrier::complete_tx::bytes [%0], [%1, {%3, %4}], [%2];" ::"r"(dst), "l"(m), "r"(bar), "r"(c0), "r"(c1) : "memory");
}
__device__ __forceinline__ uint64_t pol_ef() { uint64_t p; asm("createpolicy.fractional.L2::evict_first.b64 %0, 1.0;" : "=l"(p)); return p; }
__device__ __forceinline__ void tma3d_ef(uint32_t dst, const CUtensorMap* m, int c1, int c2, uint32_t bar) {
  asm volatile("cp.async.bulk.tensor.3d.shared::cluster.global.mbarrier::complete_tx::bytes.L2::cache_hint [%0], [%1, {%3, %4, %5}], [%2], %6;" ::"r"(dst), "l"(m), "r"(bar), "r"(0), "r"(c1), "r"(c2), "l"(pol_ef()) : "memory");
}
__device__ __forceinline__ void tma4d_ef(uint32_t dst, const CUtensorMap* m, int c1, int c2, int c3, uint32_t bar) {
  asm volatile("cp.async.bulk.tensor.4d.shared::cluster.global.mbarrier::complete_tx::bytes.L2::cache_hint [%0], [%1, {%3, %7, %4, %5}], [%2], %6;" ::"r"(dst), "l"(m), "r"(bar), "r"(0), "r"(c2), "r"(c3), "l"(pol_ef()), "r"(c1) : "memory");
}
__device__ __forceinline__ void bulk_ld(uint32_t dst, const void* src, int bytes, uint32_t bar) {
  asm volatile("cp.async.bulk.shared::cluster.global.mbarrier::complete_tx::bytes [%0], [%1], %2, [%3];" ::"r"(dst), "l"(src), "r"(bytes), "r"(bar) : "memory");
}
__device__ __forceinline__ void bulk_st(void* dst, uint32_t src, int bytes) {
  asm volatile("cp.async.bulk.global.shared::cta.bulk_group [%0], [%1], %2;" ::"l"(dst), "r"(src), "r"(bytes) : "memory");
}
__device__ __forceinline__ void tma_st2d(const CUtensorMap* m, uint32_t src, int c0, int c1) {
  asm volatile("cp.async.bulk.tensor.2d.global.shared::cta.bulk_group [%0, {%2, %3}], [%1];" ::"l"(m), "r"(src), "r"(c0), "r"(c1) : "memory");
}
__device__ __forceinline__ void tma_st3d(const CUtensorMap* m, uint32_t src, int c0, int c1, int c2) {
  asm volatile("cp.async.bulk.tensor.3d.global.shared::cta.bulk_group [%0, {%2, %3, %4}], [%1];" ::"l"(m), "r"(src), "r"(c0), "r"(c1), "r"(c2) : "memory");
}
__device__ __forceinline__ void bulk_commit_wait_read() {
  asm volatile("cp.async.bulk.commit_group;" ::: "memory");
  asm volatile("cp.async.bulk.wait_group.read 0;" ::: "memory");
}
__device__ __forceinline__ void bulk_commit_wait() {
  asm volatile("cp.async.bulk.commit_group;" ::: "memory");
  asm volatile("cp.async.bulk.wait_group 0;" ::: "memory");
}
__device__ __forceinline__ void prefetch_l2(const void* p, int bytes) {
  asm volatile("cp.async.bulk.prefetch.L2.global [%0], %1;" ::"l"(p), "r"(bytes) : "memory");
}
__device__ __forceinline__ void wg_fence() { asm volatile("wgmma.fence.sync.aligned;" ::: "memory"); }
__device__ __forceinline__ void wg_commit() { asm volatile("wgmma.commit_group.sync.aligned;" ::: "memory"); }
template <int N> __device__ __forceinline__ void wg_wait() { asm volatile("wgmma.wait_group.sync.aligned %0;" ::"n"(N) : "memory"); }
template <int N> __device__ __forceinline__ void reg_fence(float (&d)[N]) {
#pragma unroll
  for (int i = 0; i < N; i++) asm volatile("" : "+f"(d[i])::"memory");
}
__device__ __forceinline__ void fence_async_smem() { asm volatile("fence.proxy.async.shared::cta;" ::: "memory"); }
__device__ __forceinline__ void fence_async_glb() { asm volatile("fence.proxy.async.global;" ::: "memory"); }
__device__ __forceinline__ uint32_t ld_rlx(const void* p) { uint32_t v; asm volatile("ld.relaxed.gpu.global.b32 %0, [%1];" : "=r"(v) : "l"(p) : "memory"); return v; }
__device__ __forceinline__ uint2 ld_rlx2(const void* p) { uint2 v; asm volatile("ld.relaxed.gpu.global.v2.b32 {%0,%1}, [%2];" : "=r"(v.x), "=r"(v.y) : "l"(p) : "memory"); return v; }
__device__ __forceinline__ uint4 ld_rlx4(const void* p) { uint4 v; asm volatile("ld.relaxed.gpu.global.v4.b32 {%0,%1,%2,%3}, [%4];" : "=r"(v.x), "=r"(v.y), "=r"(v.z), "=r"(v.w) : "l"(p) : "memory"); return v; }
__device__ __forceinline__ uint32_t ld_nc(const void* p) { uint32_t v; asm volatile("ld.global.nc.L1::no_allocate.b32 %0, [%1];" : "=r"(v) : "l"(p) : "memory"); return v; }
__device__ __forceinline__ uint32_t lds(uint32_t a) { uint32_t v; asm volatile("ld.shared.b32 %0, [%1];" : "=r"(v) : "r"(a) : "memory"); return v; }
__device__ __forceinline__ uint2 lds2(uint32_t a) { uint2 v; asm volatile("ld.shared.v2.b32 {%0,%1}, [%2];" : "=r"(v.x), "=r"(v.y) : "r"(a) : "memory"); return v; }
__device__ __forceinline__ uint4 lds4(uint32_t a) { uint4 v; asm volatile("ld.shared.v4.b32 {%0,%1,%2,%3}, [%4];" : "=r"(v.x), "=r"(v.y), "=r"(v.z), "=r"(v.w) : "r"(a) : "memory"); return v; }
__device__ __forceinline__ float lds_bf(uint32_t a) { uint32_t v; asm volatile("ld.shared.u16 %0, [%1];" : "=r"(v) : "r"(a) : "memory"); return __uint_as_float(v << 16); }
__device__ __forceinline__ void sts(uint32_t a, uint32_t v) { asm volatile("st.shared.b32 [%0], %1;" ::"r"(a), "r"(v) : "memory"); }
__device__ __forceinline__ void sts2(uint32_t a, uint32_t v0, uint32_t v1) { asm volatile("st.shared.v2.b32 [%0], {%1,%2};" ::"r"(a), "r"(v0), "r"(v1) : "memory"); }
__device__ __forceinline__ void sts4(uint32_t a, uint32_t v0, uint32_t v1, uint32_t v2, uint32_t v3) { asm volatile("st.shared.v4.b32 [%0], {%1,%2,%3,%4};" ::"r"(a), "r"(v0), "r"(v1), "r"(v2), "r"(v3) : "memory"); }
__device__ __forceinline__ void bar_sync(int id, int n) { asm volatile("bar.sync %0, %1;" ::"r"(id), "r"(n) : "memory"); }
__device__ __forceinline__ void bar_arrive(int id, int n) { asm volatile("bar.arrive %0, %1;" ::"r"(id), "r"(n) : "memory"); }
__device__ __forceinline__ void red_add(unsigned* p, unsigned v) { asm volatile("red.relaxed.gpu.global.add.u32 [%0], %1;" ::"l"(p), "r"(v) : "memory"); }
__device__ __forceinline__ bool any(bool p) { return __any_sync(0xffffffffu, p); }
constexpr int SPIN_MAX = 1 << 20;
__device__ __forceinline__ void wait_cnt(const unsigned* p, unsigned target) {
  int it = 0;
  while (any((int)(ld_rlx(p) - target) < 0) && ++it < SPIN_MAX) {}
}
__device__ __forceinline__ uint32_t pack_bf16(float lo, float hi) { uint32_t r; asm("cvt.rn.bf16x2.f32 %0, %1, %2;" : "=r"(r) : "f"(hi), "f"(lo)); return r; }
__device__ __forceinline__ float bf_lo(uint32_t v) { return __uint_as_float(v << 16); }
__device__ __forceinline__ float bf_hi(uint32_t v) { return __uint_as_float(v & 0xffff0000u); }
__device__ __forceinline__ uint32_t hadd2(uint32_t a, uint32_t b) { uint32_t r; asm("add.rn.bf16x2 %0, %1, %2;" : "=r"(r) : "r"(a), "r"(b)); return r; }
__device__ __forceinline__ uint32_t hmul2(uint32_t a, uint32_t b) { uint32_t r; asm("mul.rn.bf16x2 %0, %1, %2;" : "=r"(r) : "r"(a), "r"(b)); return r; }
__device__ __forceinline__ uint32_t hfma2(uint32_t a, uint32_t b, uint32_t c) { uint32_t r; asm("fma.rn.bf16x2 %0, %1, %2, %3;" : "=r"(r) : "r"(a), "r"(b), "r"(c)); return r; }
__device__ __forceinline__ float rbf(float x) { uint32_t r; asm("cvt.rn.bf16x2.f32 %0, %1, %2;" : "=r"(r) : "f"(x), "f"(0.0f)); return __uint_as_float(r); }
__device__ __forceinline__ void stmatrix4(uint32_t a, uint32_t r0, uint32_t r1, uint32_t r2, uint32_t r3) {
  asm volatile("stmatrix.sync.aligned.m8n8.x4.shared.b16 [%0], {%1,%2,%3,%4};" ::"r"(a), "r"(r0), "r"(r1), "r"(r2), "r"(r3) : "memory");
}
__device__ __forceinline__ void stmatrix2(uint32_t a, uint32_t r0, uint32_t r1) {
  asm volatile("stmatrix.sync.aligned.m8n8.x2.shared.b16 [%0], {%1,%2};" ::"r"(a), "r"(r0), "r"(r1) : "memory");
}
__device__ __forceinline__ void stmatrix4t(uint32_t a, uint32_t r0, uint32_t r1, uint32_t r2, uint32_t r3) {
  asm volatile("stmatrix.sync.aligned.m8n8.x4.trans.shared.b16 [%0], {%1,%2,%3,%4};" ::"r"(a), "r"(r0), "r"(r1), "r"(r2), "r"(r3) : "memory");
}
__device__ __forceinline__ uint32_t movm(uint32_t a) { uint32_t r; asm("movmatrix.sync.aligned.m8n8.trans.b16 %0, %1;" : "=r"(r) : "r"(a)); return r; }
template <bool ACC> __device__ __forceinline__ void mma16(float* d, uint32_t a0, uint32_t a1, uint32_t a2, uint32_t a3, uint32_t b0, uint32_t b1) {
  if (ACC) asm("mma.sync.aligned.m16n8k16.row.col.f32.bf16.bf16.f32 {%0,%1,%2,%3}, {%4,%5,%6,%7}, {%8,%9}, {%0,%1,%2,%3};"
               : "+f"(d[0]), "+f"(d[1]), "+f"(d[2]), "+f"(d[3]) : "r"(a0), "r"(a1), "r"(a2), "r"(a3), "r"(b0), "r"(b1));
  else asm("mma.sync.aligned.m16n8k16.row.col.f32.bf16.bf16.f32 {%0,%1,%2,%3}, {%4,%5,%6,%7}, {%8,%9}, {%10,%10,%10,%10};"
           : "=f"(d[0]), "=f"(d[1]), "=f"(d[2]), "=f"(d[3]) : "r"(a0), "r"(a1), "r"(a2), "r"(a3), "r"(b0), "r"(b1), "f"(0.f));
}
__device__ __forceinline__ uint32_t pin(uint32_t v) { uint32_t r; asm volatile("shfl.sync.bfly.b32 %0, %1, 0, 31, 0xffffffff;" : "=r"(r) : "r"(v)); return r; }
template <class T> __device__ __forceinline__ T* pin(T* p) {
  const uint64_t a = reinterpret_cast<uint64_t>(p);
  return reinterpret_cast<T*>((uint64_t)pin((uint32_t)a) | ((uint64_t)pin((uint32_t)(a >> 32)) << 32));
}
__device__ __forceinline__ uint32_t upin(uint32_t v) { return __shfl_sync(0xffffffffu, v, 0); }
template <class T> __device__ __forceinline__ T* upin(T* p) {
  const uint64_t a = reinterpret_cast<uint64_t>(p);
  return reinterpret_cast<T*>((uint64_t)upin((uint32_t)a) | ((uint64_t)upin((uint32_t)(a >> 32)) << 32));
}
__device__ __forceinline__ bool elect() {
  uint32_t p;
  asm volatile("{\n.reg .pred P;\nelect.sync _|P, 0xffffffff;\nselp.u32 %0, 1, 0, P;\n}" : "=r"(p));
  return p;
}
__device__ __forceinline__ uint32_t set_tag(uint32_t w, uint32_t tag) { uint32_t r; asm("lop3.b32 %0, %1, 0xfffffffe, %2, 0xea;" : "=r"(r) : "r"(w), "r"(tag)); return r; }
__device__ __forceinline__ uint32_t diff2(uint32_t a, uint32_t b, uint32_t tag) { uint32_t r; asm("lop3.b32 %0, %1, %2, %3, 0x7e;" : "=r"(r) : "r"(a), "r"(b), "r"(tag)); return r; }
__device__ __forceinline__ float2 cmul(float2 a, float2 b) { return make_float2(a.x * b.x - a.y * b.y, a.x * b.y + a.y * b.x); }

template<int TB> __device__ __forceinline__ void wgmma_ss_160_0(float (&d)[80], uint32_t al, uint32_t ah, uint32_t bl, uint32_t bh) {
  asm volatile("{\n.reg .b64 da, db;\nmov.b64 da, {%80, %81};\nmov.b64 db, {%82, %83};\n"
    "wgmma.mma_async.sync.aligned.m64n160k16.f32.bf16.bf16 {%0,%1,%2,%3,%4,%5,%6,%7,%8,%9,%10,%11,%12,%13,%14,%15,%16,%17,%18,%19,%20,%21,%22,%23,%24,%25,%26,%27,%28,%29,%30,%31,%32,%33,%34,%35,%36,%37,%38,%39,%40,%41,%42,%43,%44,%45,%46,%47,%48,%49,%50,%51,%52,%53,%54,%55,%56,%57,%58,%59,%60,%61,%62,%63,%64,%65,%66,%67,%68,%69,%70,%71,%72,%73,%74,%75,%76,%77,%78,%79}, da, db, 1, 1, 1, 1, %84;\n}\n"
    : "+f"(d[0]),"+f"(d[1]),"+f"(d[2]),"+f"(d[3]),"+f"(d[4]),"+f"(d[5]),"+f"(d[6]),"+f"(d[7]),"+f"(d[8]),"+f"(d[9]),"+f"(d[10]),"+f"(d[11]),"+f"(d[12]),"+f"(d[13]),"+f"(d[14]),"+f"(d[15]),"+f"(d[16]),"+f"(d[17]),"+f"(d[18]),"+f"(d[19]),"+f"(d[20]),"+f"(d[21]),"+f"(d[22]),"+f"(d[23]),"+f"(d[24]),"+f"(d[25]),"+f"(d[26]),"+f"(d[27]),"+f"(d[28]),"+f"(d[29]),"+f"(d[30]),"+f"(d[31]),"+f"(d[32]),"+f"(d[33]),"+f"(d[34]),"+f"(d[35]),"+f"(d[36]),"+f"(d[37]),"+f"(d[38]),"+f"(d[39]),"+f"(d[40]),"+f"(d[41]),"+f"(d[42]),"+f"(d[43]),"+f"(d[44]),"+f"(d[45]),"+f"(d[46]),"+f"(d[47]),"+f"(d[48]),"+f"(d[49]),"+f"(d[50]),"+f"(d[51]),"+f"(d[52]),"+f"(d[53]),"+f"(d[54]),"+f"(d[55]),"+f"(d[56]),"+f"(d[57]),"+f"(d[58]),"+f"(d[59]),"+f"(d[60]),"+f"(d[61]),"+f"(d[62]),"+f"(d[63]),"+f"(d[64]),"+f"(d[65]),"+f"(d[66]),"+f"(d[67]),"+f"(d[68]),"+f"(d[69]),"+f"(d[70]),"+f"(d[71]),"+f"(d[72]),"+f"(d[73]),"+f"(d[74]),"+f"(d[75]),"+f"(d[76]),"+f"(d[77]),"+f"(d[78]),"+f"(d[79])
    : "r"(al), "r"(ah), "r"(bl), "r"(bh), "n"(TB));
}
template<int TB> __device__ __forceinline__ void wgmma_ss_144_0(float (&d)[80], uint32_t al, uint32_t ah, uint32_t bl, uint32_t bh) {
  asm volatile("{\n.reg .b64 da, db;\nmov.b64 da, {%72, %73};\nmov.b64 db, {%74, %75};\n"
    "wgmma.mma_async.sync.aligned.m64n144k16.f32.bf16.bf16 {%0,%1,%2,%3,%4,%5,%6,%7,%8,%9,%10,%11,%12,%13,%14,%15,%16,%17,%18,%19,%20,%21,%22,%23,%24,%25,%26,%27,%28,%29,%30,%31,%32,%33,%34,%35,%36,%37,%38,%39,%40,%41,%42,%43,%44,%45,%46,%47,%48,%49,%50,%51,%52,%53,%54,%55,%56,%57,%58,%59,%60,%61,%62,%63,%64,%65,%66,%67,%68,%69,%70,%71}, da, db, 1, 1, 1, 1, %76;\n}\n"
    : "+f"(d[0]),"+f"(d[1]),"+f"(d[2]),"+f"(d[3]),"+f"(d[4]),"+f"(d[5]),"+f"(d[6]),"+f"(d[7]),"+f"(d[8]),"+f"(d[9]),"+f"(d[10]),"+f"(d[11]),"+f"(d[12]),"+f"(d[13]),"+f"(d[14]),"+f"(d[15]),"+f"(d[16]),"+f"(d[17]),"+f"(d[18]),"+f"(d[19]),"+f"(d[20]),"+f"(d[21]),"+f"(d[22]),"+f"(d[23]),"+f"(d[24]),"+f"(d[25]),"+f"(d[26]),"+f"(d[27]),"+f"(d[28]),"+f"(d[29]),"+f"(d[30]),"+f"(d[31]),"+f"(d[32]),"+f"(d[33]),"+f"(d[34]),"+f"(d[35]),"+f"(d[36]),"+f"(d[37]),"+f"(d[38]),"+f"(d[39]),"+f"(d[40]),"+f"(d[41]),"+f"(d[42]),"+f"(d[43]),"+f"(d[44]),"+f"(d[45]),"+f"(d[46]),"+f"(d[47]),"+f"(d[48]),"+f"(d[49]),"+f"(d[50]),"+f"(d[51]),"+f"(d[52]),"+f"(d[53]),"+f"(d[54]),"+f"(d[55]),"+f"(d[56]),"+f"(d[57]),"+f"(d[58]),"+f"(d[59]),"+f"(d[60]),"+f"(d[61]),"+f"(d[62]),"+f"(d[63]),"+f"(d[64]),"+f"(d[65]),"+f"(d[66]),"+f"(d[67]),"+f"(d[68]),"+f"(d[69]),"+f"(d[70]),"+f"(d[71])
    : "r"(al), "r"(ah), "r"(bl), "r"(bh), "n"(TB));
}
template<int TB> __device__ __forceinline__ void wgmma_ss_96_0(float (&d)[80], uint32_t al, uint32_t ah, uint32_t bl, uint32_t bh) {
  asm volatile("{\n.reg .b64 da, db;\nmov.b64 da, {%48, %49};\nmov.b64 db, {%50, %51};\n"
    "wgmma.mma_async.sync.aligned.m64n96k16.f32.bf16.bf16 {%0,%1,%2,%3,%4,%5,%6,%7,%8,%9,%10,%11,%12,%13,%14,%15,%16,%17,%18,%19,%20,%21,%22,%23,%24,%25,%26,%27,%28,%29,%30,%31,%32,%33,%34,%35,%36,%37,%38,%39,%40,%41,%42,%43,%44,%45,%46,%47}, da, db, 1, 1, 1, 1, %52;\n}\n"
    : "+f"(d[0]),"+f"(d[1]),"+f"(d[2]),"+f"(d[3]),"+f"(d[4]),"+f"(d[5]),"+f"(d[6]),"+f"(d[7]),"+f"(d[8]),"+f"(d[9]),"+f"(d[10]),"+f"(d[11]),"+f"(d[12]),"+f"(d[13]),"+f"(d[14]),"+f"(d[15]),"+f"(d[16]),"+f"(d[17]),"+f"(d[18]),"+f"(d[19]),"+f"(d[20]),"+f"(d[21]),"+f"(d[22]),"+f"(d[23]),"+f"(d[24]),"+f"(d[25]),"+f"(d[26]),"+f"(d[27]),"+f"(d[28]),"+f"(d[29]),"+f"(d[30]),"+f"(d[31]),"+f"(d[32]),"+f"(d[33]),"+f"(d[34]),"+f"(d[35]),"+f"(d[36]),"+f"(d[37]),"+f"(d[38]),"+f"(d[39]),"+f"(d[40]),"+f"(d[41]),"+f"(d[42]),"+f"(d[43]),"+f"(d[44]),"+f"(d[45]),"+f"(d[46]),"+f"(d[47])
    : "r"(al), "r"(ah), "r"(bl), "r"(bh), "n"(TB));
}
template<int TB> __device__ __forceinline__ void wgmma_ss_48_48(float (&d)[80], uint32_t al, uint32_t ah, uint32_t bl, uint32_t bh) {
  asm volatile("{\n.reg .b64 da, db;\nmov.b64 da, {%24, %25};\nmov.b64 db, {%26, %27};\n"
    "wgmma.mma_async.sync.aligned.m64n48k16.f32.bf16.bf16 {%0,%1,%2,%3,%4,%5,%6,%7,%8,%9,%10,%11,%12,%13,%14,%15,%16,%17,%18,%19,%20,%21,%22,%23}, da, db, 1, 1, 1, 1, %28;\n}\n"
    : "+f"(d[48]),"+f"(d[49]),"+f"(d[50]),"+f"(d[51]),"+f"(d[52]),"+f"(d[53]),"+f"(d[54]),"+f"(d[55]),"+f"(d[56]),"+f"(d[57]),"+f"(d[58]),"+f"(d[59]),"+f"(d[60]),"+f"(d[61]),"+f"(d[62]),"+f"(d[63]),"+f"(d[64]),"+f"(d[65]),"+f"(d[66]),"+f"(d[67]),"+f"(d[68]),"+f"(d[69]),"+f"(d[70]),"+f"(d[71])
    : "r"(al), "r"(ah), "r"(bl), "r"(bh), "n"(TB));
}
__device__ __forceinline__ void wgmma_rs_72(float (&d)[36], uint32_t a0, uint32_t a1, uint32_t a2, uint32_t a3, uint32_t bl, uint32_t bh, int sd) {
  asm volatile("{\n.reg .pred p;\n.reg .b64 db;\nsetp.ne.b32 p, %42, 0;\nmov.b64 db, {%40, %41};\n"
    "wgmma.mma_async.sync.aligned.m64n72k16.f32.bf16.bf16 {%0,%1,%2,%3,%4,%5,%6,%7,%8,%9,%10,%11,%12,%13,%14,%15,%16,%17,%18,%19,%20,%21,%22,%23,%24,%25,%26,%27,%28,%29,%30,%31,%32,%33,%34,%35}, {%36,%37,%38,%39}, db, p, 1, 1, 1;\n}\n"
    : "+f"(d[0]),"+f"(d[1]),"+f"(d[2]),"+f"(d[3]),"+f"(d[4]),"+f"(d[5]),"+f"(d[6]),"+f"(d[7]),"+f"(d[8]),"+f"(d[9]),"+f"(d[10]),"+f"(d[11]),"+f"(d[12]),"+f"(d[13]),"+f"(d[14]),"+f"(d[15]),"+f"(d[16]),"+f"(d[17]),"+f"(d[18]),"+f"(d[19]),"+f"(d[20]),"+f"(d[21]),"+f"(d[22]),"+f"(d[23]),"+f"(d[24]),"+f"(d[25]),"+f"(d[26]),"+f"(d[27]),"+f"(d[28]),"+f"(d[29]),"+f"(d[30]),"+f"(d[31]),"+f"(d[32]),"+f"(d[33]),"+f"(d[34]),"+f"(d[35])
    : "r"(a0), "r"(a1), "r"(a2), "r"(a3), "r"(bl), "r"(bh), "r"(sd));
}
__device__ __forceinline__ void wgmma_rs_48(float (&d)[24], uint32_t a0, uint32_t a1, uint32_t a2, uint32_t a3, uint32_t bl, uint32_t bh, int sd) {
  asm volatile("{\n.reg .pred p;\n.reg .b64 db;\nsetp.ne.b32 p, %30, 0;\nmov.b64 db, {%28, %29};\n"
    "wgmma.mma_async.sync.aligned.m64n48k16.f32.bf16.bf16 {%0,%1,%2,%3,%4,%5,%6,%7,%8,%9,%10,%11,%12,%13,%14,%15,%16,%17,%18,%19,%20,%21,%22,%23}, {%24,%25,%26,%27}, db, p, 1, 1, 1;\n}\n"
    : "+f"(d[0]),"+f"(d[1]),"+f"(d[2]),"+f"(d[3]),"+f"(d[4]),"+f"(d[5]),"+f"(d[6]),"+f"(d[7]),"+f"(d[8]),"+f"(d[9]),"+f"(d[10]),"+f"(d[11]),"+f"(d[12]),"+f"(d[13]),"+f"(d[14]),"+f"(d[15]),"+f"(d[16]),"+f"(d[17]),"+f"(d[18]),"+f"(d[19]),"+f"(d[20]),"+f"(d[21]),"+f"(d[22]),"+f"(d[23])
    : "r"(a0), "r"(a1), "r"(a2), "r"(a3), "r"(bl), "r"(bh), "r"(sd));
}
template<int N,int OFF,int TB> __device__ __forceinline__ void wgmma_ss(float (&d)[80], uint32_t al, uint32_t ah, uint32_t bl, uint32_t bh) {
  if constexpr (N==160) wgmma_ss_160_0<TB>(d, al, ah, bl, bh);
  else if constexpr (N==144) wgmma_ss_144_0<TB>(d, al, ah, bl, bh);
  else if constexpr (N==96) wgmma_ss_96_0<TB>(d, al, ah, bl, bh);
  else if constexpr (N==48) wgmma_ss_48_48<TB>(d, al, ah, bl, bh);
}

__device__ __forceinline__ void dft3(float2& a, float2& b, float2& c) {
  const float s = 0.86602540378443864676f;
  float2 t = make_float2(b.x + c.x, b.y + c.y), d = make_float2(b.x - c.x, b.y - c.y);
  float2 m = make_float2(fmaf(-0.5f, t.x, a.x), fmaf(-0.5f, t.y, a.y));
  a = make_float2(a.x + t.x, a.y + t.y);
  b = make_float2(fmaf(s, d.y, m.x), fmaf(-s, d.x, m.y));
  c = make_float2(fmaf(-s, d.y, m.x), fmaf(s, d.x, m.y));
}
__device__ __forceinline__ void dft9(float2 (&x)[9]) {
  const float2 w1 = make_float2(0.76604444311897803520f, -0.64278760968653932632f);
  const float2 w2 = make_float2(0.17364817766693034885f, -0.98480775301220805937f);
  const float2 w4 = make_float2(-0.93969262078590838405f, -0.34202014332566873304f);
  dft3(x[0], x[3], x[6]); dft3(x[1], x[4], x[7]); dft3(x[2], x[5], x[8]);
  x[4] = cmul(x[4], w1); x[7] = cmul(x[7], w2); x[5] = cmul(x[5], w2); x[8] = cmul(x[8], w4);
  dft3(x[0], x[1], x[2]); dft3(x[3], x[4], x[5]); dft3(x[6], x[7], x[8]);
  float2 t;
  t = x[1]; x[1] = x[3]; x[3] = t;
  t = x[2]; x[2] = x[6]; x[6] = t;
  t = x[5]; x[5] = x[7]; x[7] = t;
}

__device__ __forceinline__ int mod_pos(int u, int i) { return 16 * u + (u < 72 ? 2 * (i & 7) + (i >> 3) : i); }
__device__ __forceinline__ void mod_fma(float (&acc)[8], float sc, const uint4& w) {
  acc[0] = fmaf(sc, bf_lo(w.x), acc[0]); acc[1] = fmaf(sc, bf_hi(w.x), acc[1]);
  acc[2] = fmaf(sc, bf_lo(w.y), acc[2]); acc[3] = fmaf(sc, bf_hi(w.y), acc[3]);
  acc[4] = fmaf(sc, bf_lo(w.z), acc[4]); acc[5] = fmaf(sc, bf_hi(w.z), acc[5]);
  acc[6] = fmaf(sc, bf_lo(w.w), acc[6]); acc[7] = fmaf(sc, bf_hi(w.w), acc[7]);
}
__device__ __forceinline__ void mod_finish(const Params& p, float (&acc)[8], int u, int t128, uint32_t rb, uint32_t tag) {
#pragma unroll
  for (int n = 4, o = 2; n; n >>= 1, o <<= 1) {
    const bool up = t128 & o;
#pragma unroll
    for (int e = 0; e < n; e++) acc[e] = (up ? acc[e + n] : acc[e]) + __shfl_xor_sync(0xffffffffu, up ? acc[e] : acc[e + n], o);
  }
  acc[0] += __shfl_xor_sync(0xffffffffu, acc[0], 16);
  const int col = 8 * (t128 & 1) + 2 * (t128 & 2) + ((t128 >> 1) & 2) + ((t128 >> 3) & 1);
  if (!(t128 & 16)) sts(rb + (col * 4 + (t128 >> 5)) * 4, __float_as_uint(acc[0]));
  bar_sync(4, 128);
  if (t128 < 16) {
    const uint4 v = lds4(rb + t128 * 16);
    float m = rbf((__uint_as_float(v.x) + __uint_as_float(v.y)) + (__uint_as_float(v.z) + __uint_as_float(v.w)));
    const int kind = u / 36;
    if (kind == 0) m *= 16.0f;
    if (kind == 1 || kind == 4) m = rbf(1.0f + m);
    p.s->mod[mod_pos(u, t128)] = __float_as_uint(m) | tag;
  }
}

__device__ __forceinline__ void ln_stats2(const float (&a)[18], const float (&b)[18], float sc, float& oa, float& ra, float& ob, float& rb) {
  float v[4] = {0.f, 0.f, 0.f, 0.f}, w[4] = {0.f, 0.f, 0.f, 0.f};
#pragma unroll
  for (int i = 0; i < 18; i += 2) {
    v[0] += a[i]; v[1] = fmaf(a[i], a[i], v[1]); v[2] += b[i]; v[3] = fmaf(b[i], b[i], v[3]);
    w[0] += a[i + 1]; w[1] = fmaf(a[i + 1], a[i + 1], w[1]); w[2] += b[i + 1]; w[3] = fmaf(b[i + 1], b[i + 1], w[3]);
  }
#pragma unroll
  for (int e = 0; e < 4; e++) v[e] += w[e];
#pragma unroll
  for (int o = 16; o; o >>= 1) {
#pragma unroll
    for (int e = 0; e < 4; e++) v[e] += __shfl_xor_sync(0xffffffffu, v[e], o);
  }
  const float ma = v[0] * (1.0f / D_), mb = v[2] * (1.0f / D_);
  ra = sc * rsqrtf(fmaxf(fmaf(-ma, ma, v[1] * (1.0f / D_)), 0.f) + 1e-5f);
  rb = sc * rsqrtf(fmaxf(fmaf(-mb, mb, v[3] * (1.0f / D_)), 0.f) + 1e-5f);
  oa = -ma * ra; ob = -mb * rb;
}

__device__ __forceinline__ float tmat(int c, int q, int j) {
  const int ph = q == 1 ? 1024 * j : (q >> 1) * (c + 128 * j) + 512 * (q & 1);
  return __cosf((float)(((ph + 1024) & 2047) - 1024) * (6.283185307179586f / 2048.0f));
}
__device__ __forceinline__ uint32_t line_off(int k1, int kap, int pi, int f) {
  int kd = 64 * k1 + 9 * kap;
  if (kap == 0 && k1 > 4) kd -= 288;
  if (kd >= D_) kd -= D_;
  return pi * 2400 + ((min(kd, D_ - kd) ^ f) << 3);
}

constexpr int JSK = 5;
struct Ring { uint32_t st, ph; };
template <bool G2, class T> __device__ __forceinline__ void ring_next(T& st, T& ph) {
  if (++st == NST) st = 0;
  ph ^= ((G2 ? 0xDu : 0x1u) >> st) & 1;
}
__device__ __forceinline__ void arrive_if(uint32_t a, uint32_t p) {
  asm volatile("{\n.reg .pred p;\nsetp.ne.u32 p, %1, 0;\n@p mbarrier.arrive.shared::cta.b64 _, [%0];\n}" ::"r"(a), "r"(p) : "memory");
}
template <int NA> __device__ __forceinline__ void reg_fence_n(float (&d)[80]) {
#pragma unroll
  for (int i = 0; i < NA; i++) asm volatile("" : "+f"(d[i])::"memory");
}
template <int MODE>
__device__ __forceinline__ void gemm_main(float (&acc)[80], uint32_t da0, uint32_t da1, uint32_t db0, uint32_t db1, int wg, Ring& rg,
                                          uint32_t* x1p, const uint32_t (&xr)[18]) {
  static_assert(JSK == NST - 1, "the held slot is the first one that is not refilled by GEMM1");
  constexpr int NKB = MODE == 3 ? 36 : 32;
  constexpr uint32_t HA = 0x40000040u, HB = MODE == 3 ? 0x40000040u : 0x80000020u;
  constexpr uint32_t KA = 2048 >> 4, KB = MODE == 3 ? (32 >> 4) : (1024 >> 4);
  constexpr int NA = MODE ? 72 : 80;
  const uint32_t t = threadIdx.x & 127;
  const uint32_t eb = full0 + 8 * NST;
  uint32_t pb = 0, rel = t == 0, prel = 0, ok = 0;
  int n = MODE == 3 ? NKB - JSK : X1K + 2 * wg;
#pragma unroll 1
  for (int pass = MODE == 3 ? 0 : -1;; pass++) {
#pragma unroll 1
    do {
      const uint32_t so = rg.st * (STAGE >> 4), cb = eb + 8 * rg.st;
      if (__builtin_expect(!ok, 0)) mbar_wait(full0 + 8 * rg.st, rg.ph);
      reg_fence_n<NA>(acc);
      wg_fence();
#pragma unroll
      for (int k = 0; k < 4; k++) {
        if (k == 3) { ring_next<MODE == 3>(rg.st, rg.ph); ok = PEEK ? mbar_test(full0 + 8 * rg.st, rg.ph) : 0; }
        if (MODE == 0) wgmma_ss<160, 0, 1>(acc, da0 + so + k * KA, HA, db0 + so + k * KB, HB);
        else if (MODE == 3) wgmma_ss<144, 0, 0>(acc, da0 + so + k * KA, HA, db0 + so + k * KB, HB);
        else {
          wgmma_ss<96, 0, 1>(acc, da0 + so + k * KA, HA, db0 + so + k * KB, HB);
          wgmma_ss<48, 48, 1>(acc, da1 + so + k * KA, HA, db1 + so + k * KB, HB);
        }
      }
      wg_commit();
      wg_wait<1>();
      reg_fence_n<NA>(acc);
      arrive_if(pb, prel);
      pb = cb; prel = rel;
    } while (--n);
    if (pass == 2 - wg) break;
    if (MODE != 3 && pass < 0) {
      if (blockIdx.x < 128) {
#pragma unroll
        for (int i = 0; i < 9; i++) { x1p[32 * i] = xr[i]; x1p[128 * 288 + 32 * i] = xr[9 + i]; }
      }
      n = NKB - JSK - X1K - 2 * wg;
      continue;
    }
    n = 1;
    if (pass == 0) {
      if (MODE != 3) prel = rel & wg;
      else rel = 0;
      n = JSK - 1 + wg;
      if (!wg) continue;
      wg_wait<0>();
      arrive_if(pb, prel);
      prel = 0;
    }
    bar_sync(1, 256);
  }
  wg_wait<0>();
  reg_fence_n<NA>(acc);
  if (MODE != 3) arrive_if(pb, prel & ~wg);
}

__device__ __forceinline__ float gelu_arg(float h) { return h * fmaf(8.0f * 0.044715f * 0.7978845608028654f, h * h, 2.0f * 0.7978845608028654f); }

__device__ __forceinline__ int kb2_order(int i) { const int wv = i / 6; return 6 * (i - 6 * wv) + ((0x431250 >> (4 * wv)) & 7); }

__device__ __forceinline__ void wait_flags(const unsigned* base, int n, int idx, unsigned target, uint64_t& ready) {
  if ((ready >> idx) & 1) return;
  const int l = threadIdx.x & 31;
  int it = 0;
  while (true) {
    unsigned a = ld_rlx(base + l), b = l + 32 < n ? ld_rlx(base + l + 32) : target;
    ready = (uint64_t)__ballot_sync(0xffffffffu, (int)(a - target) >= 0) | ((uint64_t)__ballot_sync(0xffffffffu, (int)(b - target) >= 0) << 32);
    if (((ready >> idx) & 1) || ++it > SPIN_MAX) break;
  }
  fence_async_glb();
}

enum { B_FULL = 0, B_EMPTY = 6, B_FLT = 12, B_Z1, B_Z2, B_GO, B_S4, B_S5, B_WM, B_NUM, B_W0 = B_NUM };

__global__ void __launch_bounds__(NTHR, 1)
fused_kernel(const Params p, const __grid_constant__ Maps maps) {
  extern __shared__ __align__(1024) uint8_t smem_raw[];
  const int tid = threadIdx.x, cta = blockIdx.x, t128 = tid & 127;
  const int wp = __shfl_sync(0xffffffffu, tid >> 5, 0), wg = wp >> 2;
  const int l = tid & 31, g = l >> 2, t = l & 3;
  Scratch* const sc = p.s;
  const bool rows = cta < 128;
  const int R = cta - 12;

  uint32_t xr[18];
  uint32_t cv[9];
  const unsigned ep = ld_rlx(&sc->cnt[C_EP]) + 1;
  if (tid == 0) TS(0);
  if (wg == 2) {
#pragma unroll
    for (int i = 0; i < 9; i++) asm volatile("ld.global.nc.u16 %0, [%1];" : "=r"(cv[i]) : "l"(p.c + (t128 >> 1) + 64 * i) : "memory");
    if (wp == 9 && l < 9 && rows) {
      const int h = 9 * cta + l;
      prefetch_l2(reinterpret_cast<const uint8_t*>(p.wmod) + (size_t)(h >> 1) * (12 * D_) + (h & 1) * (2 * D_), 2 * D_);
    }
    if (t128 < 16) {
#pragma unroll 1
      for (int u = cta < 72 ? cta : 72 + cta; u < 216; u += u < 72 ? 72 : NCTA) sc->mod[mod_pos(u, t128)] = 0;
    }
    if (tid == 256 && cta < 72) {
      mbar_init(full0 + 8 * B_W0, 1);
      fence_async_smem();
      mbar_expect(full0 + 8 * B_W0, 18432);
#pragma unroll 1
      for (int i = 0; i < 3; i++) tma2d(sbase + O_P2 + i * 6144, &maps.wm, 16 * cta, 192 * i, full0 + 8 * B_W0);
    }
    if (wp == 11 && smem_u32(smem_raw) != sbase) __trap();
    if (tid == 352) {
#pragma unroll 1
      for (int i = 0; i < B_NUM; i++) mbar_init(full0 + 8 * i, i == B_FLT ? 4 : i == B_WM ? 3 : (i >= B_EMPTY && i < B_FLT) || i == B_S4 || i == B_S5 ? 2 : 1);
      fence_async_smem();
    }
    if (wp == 10 && l < 13) asm volatile("prefetch.tensormap [%0];" ::"l"(&maps.w1a + l) : "memory");
    __syncwarp();
  }
  CK(0);
  auto load_x = [&]() {
    const uint32_t* xs = reinterpret_cast<const uint32_t*>(p.x) + (size_t)(cta + 256 * wp) * 288 + l;
#pragma unroll
    for (int i = 0; i < 9; i++) { xr[i] = ld_nc(xs + 32 * i); xr[9 + i] = ld_nc(xs + 128 * 288 + 32 * i); }
  };
  if (rows && wg < 2) load_x();
  if (tid == 64 && cta == NCTA - 1) prefetch_l2(p.tab, sizeof(T_TAB));
  __syncwarp();
  const uint32_t tag16 = (ep & 0x7fffu) | 0x8000u, tag1 = ep & 1u;

  if (wg == 2) {
    float sil[9];
#pragma unroll
    for (int i = 0; i < 9; i++) sil[i] = rbf(__fdividef(bf_lo(cv[i]), 1.0f + __expf(-bf_lo(cv[i]))));
    if (cta < 72) {
      float acc[8] = {0.f, 0.f, 0.f, 0.f, 0.f, 0.f, 0.f, 0.f};
      bar_sync(4, 128);
      mbar_wait(full0 + 8 * B_W0, 0);
      if (t128 == 0) TS(10);
#pragma unroll
      for (int i = 0; i < 9; i++) mod_fma(acc, sil[i], lds4(sbase + O_P2 + t128 * 16 + i * 2048));
      mod_finish(p, acc, cta, t128, red, tag16);
      if (t128 == 0) TS(25);
    }
#pragma unroll
    for (int i = 0; i < 9; i++) sts(red + 512 + ((t128 >> 1) + 64 * i) * 4, __float_as_uint(sil[i]));
    CK(1);
  }
  const int pi = R / 15, col0 = 20 * (R - 15 * pi);
  const int xu = DF_ * pi + col0, xv = DF_ * (pi ? 16 - pi : 8) + col0;
  auto load_filter = [&](int a) {
    const int x = (a & 1) ? xv : xu;
    const bool wide = (x & 15) > 12;
    mbar_expect(full0 + 8 * B_FLT, wide ? 12288 : 8192);
    tma2d(sbase + O_RAW + a * 12288, &maps.wf[a & 2], x & ~15, 0, full0 + 8 * B_FLT);
    if (wide) tma2d(sbase + O_RAW + a * 12288 + 8192, &maps.wf[(a & 2) + 1], (x & ~15) + 32, 0, full0 + 8 * B_FLT);
  };
  const int kap = 8 * ((wp & 3) ^ (wg & 1)) + g;
  uint4 af[4];
  if (rows) {
    uint32_t tb[4];
#pragma unroll
    for (int i = 0; i < 4; i++) tb[i] = pack_bf16(tmat(cta, 8 * (i >> 1) + g, 2 * t + 8 * (i & 1)), tmat(cta, 8 * (i >> 1) + g, 2 * t + 8 * (i & 1) + 1));
    uint32_t sb1[3], lo[9];
#pragma unroll
    for (int i = 0; i < 4; i++) tb[i] = pin(tb[i]);
#pragma unroll
    for (int i = 0; i < 3; i++) {
      const int d = 48 * wp + 16 * i + (l & 15);
      sb1[i] = pin(sbase + O_B1 + (l >> 4) * 9216 + (d % 9) * 1024 + (d & 63) * 16);
    }
    const uint32_t snt = pin(sbase + O_NRM + ((l & 7) + 8 * (l >> 4)) * 1168 + (48 * wp + (l & 8)) * 2);
    if (wg < 2) {
#pragma unroll
      for (int k1 = 0; k1 < 9; k1++) lo[k1] = pin(sbase + O_Z1 + line_off(k1, kap, 4 * wg + t, cta & 3));
#pragma unroll
      for (int kk = 0; kk < 4; kk++) af[kk] = __ldg(p.tab + TB_F + kk * 128 + (t128 ^ (wg << 5)));
      float a[18], b[18];
#pragma unroll
      for (int i = 0; i < 9; i++) { a[2 * i] = bf_lo(xr[i]); a[2 * i + 1] = bf_hi(xr[i]); b[2 * i] = bf_lo(xr[9 + i]); b[2 * i + 1] = bf_hi(xr[9 + i]); }
      float oa, ra, ob, rb;
      ln_stats2(a, b, 1.0f, oa, ra, ob, rb);
      CK(1);
      const uint32_t sn = sbase + O_NRM + wp * 2336 + l * 4;
#pragma unroll
      for (int i = 0; i < 9; i++) {
        sts(sn + i * 128, pack_bf16(fmaf(a[2 * i], ra, oa), fmaf(a[2 * i + 1], ra, oa)));
        sts(sn + 1168 + i * 128, pack_bf16(fmaf(b[2 * i], rb, ob), fmaf(b[2 * i + 1], rb, ob)));
      }
      CK(2);
      bar_arrive(10, NTHR);
      bar_sync(1, 256);
      if (tid == 0) TS(2);
    } else {
      bar_sync(10, NTHR);
      CK(2);
    }
    float rs[3][8];
#pragma unroll
    for (int i = 0; i < 3; i++) {
      uint32_t a0, a1, a2, a3;
      asm volatile("ldmatrix.sync.aligned.m8n8.x4.trans.shared.b16 {%0,%1,%2,%3}, [%4];" : "=r"(a0), "=r"(a1), "=r"(a2), "=r"(a3)
                   : "r"(snt + 32 * i) : "memory");
      mma16<false>(&rs[i][0], a0, a1, a2, a3, tb[0], tb[1]);
      mma16<false>(&rs[i][4], a0, a1, a2, a3, tb[2], tb[3]);
    }
    CK(3);
    {
      uint2 ms[3], mc[3];
      const uint32_t* mp = sc->mod + 48 * wp + 2 * g;
      int it = 0;
#pragma unroll 1
      while (true) {
        uint32_t bad = 0;
#pragma unroll
        for (int i = 0; i < 3; i++) { ms[i] = ld_rlx2(mp + 16 * i); mc[i] = ld_rlx2(mp + D_ + 16 * i); }
#pragma unroll
        for (int i = 0; i < 3; i++) {
          ms[i].x ^= tag16; ms[i].y ^= tag16; mc[i].x ^= tag16; mc[i].y ^= tag16;
          bad |= ms[i].x | ms[i].y | mc[i].x | mc[i].y;
        }
        if (!any(bad & 0xffffu) || ++it > SPIN_MAX) break;
      }
      CK(4);
      if (tid == 0) TS(3);
#pragma unroll
      for (int i = 0; i < 3; i++) {
        const float c0 = __uint_as_float(mc[i].x), c1 = __uint_as_float(mc[i].y);
        const float s0 = t ? 0.f : __uint_as_float(ms[i].x), s1 = t ? 0.f : __uint_as_float(ms[i].y);
        stmatrix4(sb1[i], pack_bf16(fmaf(rs[i][0], c0, s0), rs[i][1] * c0), pack_bf16(fmaf(rs[i][2], c1, s1), rs[i][3] * c1),
                  pack_bf16(rs[i][4] * c0, rs[i][5] * c0), pack_bf16(rs[i][6] * c1, rs[i][7] * c1));
      }
    }
    fence_async_smem();
    CK(5);
    if (wg == 2) {
      bar_arrive(5, NTHR);
      if (R >= 0 && elect()) load_filter(wp - 8);
      __syncwarp();
    } else {
      bar_sync(5, NTHR);
      CK(6);
      float acc[36];
      const uint32_t db = (((sbase + O_B1 + wg * 9216) & 0x3FFFF) >> 4) | ((128 >> 4) << 16);
      wg_fence();
#pragma unroll
      for (int kk = 0; kk < 4; kk++) wgmma_rs_72(acc, af[kk].x, af[kk].y, af[kk].z, af[kk].w, db + kk * 16, 1024 >> 4, kk);
      wg_commit();
      wg_wait<0>();
      reg_fence(acc);
      CK(7);
      float2 za[9], zb[9];
#pragma unroll
      for (int i = 0; i < 9; i++) { za[i] = make_float2(acc[4 * i], acc[4 * i + 2]); zb[i] = make_float2(acc[4 * i + 1], acc[4 * i + 3]); }
      dft9(za); dft9(zb);
      if (kap == 0) {
#pragma unroll
        for (int k = 1; k < 5; k++) {
          float2 a = za[k], b = za[9 - k];
          za[k] = make_float2(a.x + b.x, a.y - b.y); za[9 - k] = make_float2(a.y + b.y, b.x - a.x);
          a = zb[k]; b = zb[9 - k];
          zb[k] = make_float2(a.x + b.x, a.y - b.y); zb[9 - k] = make_float2(a.y + b.y, b.x - a.x);
        }
        sts2(lo[0] + 288 * 8, set_tag(pack_bf16(za[0].y, 0.f), tag1), pack_bf16(zb[0].y, 0.f));
        za[0].y = 0.f; zb[0].y = 0.f;
      }
      __syncwarp();
#pragma unroll
      for (int k1 = 0; k1 < 9; k1++) sts2(lo[k1], set_tag(pack_bf16(za[k1].x, za[k1].y), tag1), pack_bf16(zb[k1].x, zb[k1].y));
      fence_async_smem();
      CK(8);
      bar_arrive(2 + wg, 160);
    }
  } else {
    __syncthreads();
  }

  if ((wp >> 1) == 4) {
    if (rows) {
      const int slot = 4 * (cta & 7) + ((cta >> 4) & 3) + 32 * (2 * (cta >> 6) + ((cta >> 3) & 1));
      const uint32_t c0 = upin(40 * slot), c1 = upin(60 * (wp - 8)), src = upin(sbase + O_Z1 + (wp - 8) * 9600);
      const CUtensorMap* mp = upin(&maps.z1);
      unsigned* hint = pin(&sc->cnt[C_Z1 + 32 * (wp - 8)]);
      bar_sync(wp - 6, 160);
      if (elect()) {
        tma_st2d(mp, src, c0, c1);
        HW();
        red_add(hint, 1);
        if (wp == 8) TS(4);
      }
    } else {
      int it = 0;
      while (any((ld_rlx(sc->mod + 36 * l) ^ tag16) & 0xffffu) && ++it < SPIN_MAX) {}
      if (elect()) { load_filter(wp - 8); load_filter(wp - 6); }
    }
    __syncwarp();
  }
  auto load_wm = [&](int u) {
    if (wp > 8 && elect()) {
      mbar_expect(full0 + 8 * B_WM, 6144);
      tma2d(sbase + O_NRM + (wp - 9) * 6144, &maps.wm, 16 * u, 192 * (wp - 9), full0 + 8 * B_WM);
    }
    __syncwarp();
  };
  if (R >= 0) {
    const int ln0 = wg < 2 ? 2 * wp : 8 + wp;
    const int nl = min(wg < 2 ? 2 : 1, DF_ - col0 - ln0);
    uint4 cf[2][4], G[4];
#pragma unroll
    for (int i = 0; i < 4; i++) {
      cf[0][i] = __ldg(p.tab + TB_P2 + i * 32 + l);
      cf[1][i] = __ldg(p.tab + TB_P2 + (pi ? i : 4 + i) * 32 + l);
      G[i] = __ldg(p.tab + TB_P2 + (8 + i) * 32 + l);
    }
    const uint32_t* zin = sc->z1 + (size_t)R * 5120;
    if (wp == 10) {
      const uint32_t* zu = upin(zin);
      if (elect()) mbar_expect(full0 + 8 * B_Z1, 20480);
      wait_cnt(&sc->cnt[C_Z1 + 32 * (pi >> 2)], 128 * ep);
      if (elect()) {
        bulk_ld(sbase + O_P2, zu, 20480, full0 + 8 * B_Z1);
        TS(12);
      }
      __syncwarp();
    }
    mbar_wait(full0 + 8 * B_FLT, 0);
    CK(9);
    float wn[16], wc[16];
#pragma unroll 1
    for (int ln = nl - 1; ln >= 0; ln--) {
      const int col = col0 + ln0 + ln, k2 = (57 * col) & 63;
      const bool cj = k2 > 32 || (k2 == 32 && col != 288);
      const float nr = ((col & 31) == 0 && col != 0 && col != 288 ? 0.5f : 1.0f) / ((float)S_ * D_), ni = cj ? -nr : nr;
#pragma unroll
      for (int i = 0; i < 16; i++) wn[i] = wc[i];
#pragma unroll
      for (int cl = 0; cl < 2; cl++) {
        const int v = cl ^ (cj && pi), e = ((v ? xv : xu) & 15) + ln0 + ln, sh = e < 32 ? 6 : 5;
        const uint32_t base = sbase + O_RAW + v * 12288 + (e < 32 ? 2 * e : 8192 - 64 + 2 * e), msk = e < 32 ? 0x30 : 0x10;
        const int dm = v ? (cj || pi ? -1 : 0) : 0;
#pragma unroll
        for (int tt = 0; tt < 4; tt++) {
          const int kc = g + 64 * (tt >> 1) + 16 * t + 8 * (tt & 1);
          uint32_t a = base + ((((cj ? -kc : kc) + dm) & 127) << sh);
          a ^= (a >> 3) & msk;
          wc[4 * tt + 2 * cl] = lds_bf(a) * nr; wc[4 * tt + 2 * cl + 1] = lds_bf(a + 24576) * ni;
        }
      }
    }
    const float al = pi ? 1.0f : 0.0f;
    CK(10);
    uint32_t off = pin(l * 160 + ((ln0 ^ (g & 3)) << 3));
    const CUtensorMap* mz2 = upin(&maps.z2);
    const uint32_t cz2 = upin(40 * R);
    unsigned* hz2 = pin(&sc->cnt[C_Z2]);
    mbar_wait(full0 + 8 * B_Z1, 0);
    CK(11);
    if (tid == 0) TS(8);
    if (wg == 2) load_wm(72 + cta);
#pragma unroll 1
    for (int ln = 0; ln < nl; ln++, off ^= 8) {
      uint2 v[4];
#pragma unroll
      for (int i = 0; i < 4; i++) v[i] = lds2(sbase + O_P2 + off + i * 5120);
      if (__builtin_expect(any((diff2(v[0].x, v[1].x, tag1) | diff2(v[2].x, v[3].x, tag1)) & 1), 0)) {
        FAILCNT(0);
        int it = 0;
        do {
#pragma unroll
          for (int i = 0; i < 4; i++) v[i] = ld_rlx2(reinterpret_cast<const uint8_t*>(zin) + off + i * 5120);
        } while (any((diff2(v[0].x, v[1].x, tag1) | diff2(v[2].x, v[3].x, tag1)) & 1) && ++it < SPIN_MAX);
      }
      float d[4][4];
      uint32_t A[8];
#pragma unroll
      for (int h = 0; h < 2; h++) {
        mma16<false>(d[2 * h], cf[0][0].x, cf[0][0].y, cf[0][0].z, cf[0][0].w, v[h].x, v[2 + h].x);
        mma16<false>(d[2 * h + 1], cf[1][0].x, cf[1][0].y, cf[1][0].z, cf[1][0].w, v[h].y, v[2 + h].y);
      }
#pragma unroll
      for (int h = 0; h < 2; h++)
#pragma unroll
        for (int L = 0; L < 2; L++) {
          const uint4 tw = cf[L][2 + h];
          const float* z = d[2 * h + L];
          const float2 z0 = cmul(make_float2(z[0], z[2]), make_float2(__uint_as_float(tw.x), __uint_as_float(tw.y)));
          const float2 z1 = cmul(make_float2(z[1], z[3]), make_float2(__uint_as_float(tw.z), __uint_as_float(tw.w)));
          A[4 * h + L] = pack_bf16(z0.x, z0.y); A[4 * h + 2 + L] = pack_bf16(z1.x, z1.y);
        }
#pragma unroll
      for (int tt = 0; tt < 4; tt++) {
        mma16<false>(d[tt], A[0], A[1], A[2], A[3], G[tt].x, G[tt].y);
        mma16<true>(d[tt], A[4], A[5], A[6], A[7], G[tt].z, G[tt].w);
      }
#pragma unroll
      for (int tt = 0; tt < 4; tt++) {
        const float ar = d[tt][0], aj = d[tt][1], br = d[tt][2], bj = d[tt][3];
        const float2 y1 = cmul(make_float2(fmaf(-al, bj, ar), fmaf(al, br, aj)), make_float2(wc[4 * tt], wc[4 * tt + 1]));
        const float2 y2 = cmul(make_float2(fmaf(al, ar, bj), fmaf(al, aj, -br)), make_float2(wc[4 * tt + 2], wc[4 * tt + 3]));
        A[2 * tt] = pack_bf16(fmaf(al, y2.x, y1.x), fmaf(-al, y2.y, -y1.y));
        A[2 * tt + 1] = pack_bf16(fmaf(al, y1.y, -y2.y), fmaf(al, y1.x, -y2.x));
      }
#pragma unroll
      for (int i = 0; i < 16; i++) wc[i] = wn[i];
#pragma unroll
      for (int tt = 0; tt < 4; tt++) {
        mma16<false>(d[tt], A[0], A[1], A[2], A[3], G[tt].x, G[tt].y);
        mma16<true>(d[tt], A[4], A[5], A[6], A[7], G[tt].z, G[tt].w);
      }
#pragma unroll
      for (int h = 0; h < 2; h++)
#pragma unroll
        for (int L = 0; L < 2; L++) {
          const uint4 tw = cf[L][2 + h];
          const float2 z0 = cmul(make_float2(d[2 * h][2 * L], d[2 * h][2 * L + 1]), make_float2(__uint_as_float(tw.x), __uint_as_float(tw.y)));
          const float2 z1 = cmul(make_float2(d[2 * h + 1][2 * L], d[2 * h + 1][2 * L + 1]), make_float2(__uint_as_float(tw.z), __uint_as_float(tw.w)));
          A[4 * h + 2 * L] = movm(pack_bf16(z0.x, z1.x)); A[4 * h + 2 * L + 1] = movm(pack_bf16(z0.y, z1.y));
        }
#pragma unroll
      for (int h = 0; h < 2; h++) {
        mma16<false>(d[0], cf[0][1].x, cf[0][1].y, cf[0][1].z, cf[0][1].w, A[4 * h], A[4 * h + 1]);
        mma16<false>(d[1], cf[1][1].x, cf[1][1].y, cf[1][1].z, cf[1][1].w, A[4 * h + 2], A[4 * h + 3]);
#pragma unroll
        for (int e = 0; e < 2; e++)
          sts2(sbase + O_P2 + off + (2 * h + e) * 5120, set_tag(pack_bf16(d[0][e], d[0][2 + e]), tag1), pack_bf16(d[1][e], d[1][2 + e]));
      }
      CK(12 + ln);
    }
    fence_async_smem();
    if (wp) bar_arrive(6, NTHR);
    else {
      bar_sync(6, NTHR);
      if (elect()) {
        tma_st2d(mz2, sbase + O_P2, cz2, 0);
        HW();
        red_add(hz2, 1);
        TS(9);
      }
      __syncwarp();
    }
  }
  if (wg == 2) {
#pragma unroll 1
    for (int u = 72 + cta, k = 0; u < 216; u += NCTA, k ^= 1) {
      if (R < 0) { fence_async_smem(); bar_sync(4, 128); load_wm(u); }
      mbar_wait(full0 + 8 * B_WM, k);
      float acc[8] = {0.f, 0.f, 0.f, 0.f, 0.f, 0.f, 0.f, 0.f};
#pragma unroll 1
      for (int i = 0; i < 9; i++) mod_fma(acc, __uint_as_float(lds(red + 512 + ((t128 >> 1) + 64 * i) * 4)), lds4(sbase + O_NRM + t128 * 16 + i * 2048));
      mod_finish(p, acc, u, t128, red + 256 - 256 * k, tag16);
    }
    fence_async_smem();
    CK(13);
  }

  const int grp = cta / 11, m1 = cta - 11 * grp;
  const bool helper = (m1 & 3) == 3;
  const int f1 = 384 * grp + (helper ? 192 : 128) * (m1 >> 2);
  const int d1 = 160 * (m1 & 3), flip = m1 >= 7;
  const int a1bytes = helper ? 24576 : 16384;
  auto load_a1 = [&](int st, int kb) {
    mbar_expect(full0 + 8 * st, STAGE);
    tma4d_ef(sbase + st * STAGE, helper ? &maps.w1b : &maps.w1a, 4 * (kb >> 3), 16 * (kb & 7), f1 >> 6, full0 + 8 * st);
  };

  if (rows) {
#pragma unroll
    for (int kk = 0; kk < 4; kk++) af[kk] = __ldg(p.tab + TB_E + kk * 128 + t128);
    uint32_t tb[4], sy[6];
#pragma unroll
    for (int i = 0; i < 4; i++) tb[i] = pack_bf16(tmat(cta, 2 * t + 8 * (i & 1), 8 * (i >> 1) + g), tmat(cta, 2 * t + 8 * (i & 1) + 1, 8 * (i >> 1) + g));
#pragma unroll
    for (int i = 0; i < 6; i++) {
      const int rr = 16 * (wp & 3) + g + 8 * (i & 1);
      sy[i] = pin(sbase + O_Y + (t * 584 + 64 * ((3 * wg + (i >> 1) + 63 - rr) % 9) + rr) * 4);
    }
#pragma unroll
    for (int i = 0; i < 4; i++) tb[i] = pin(tb[i]);
    const int slot = 4 * (cta >> 4) + ((cta >> 1) & 3) + 32 * (2 * ((cta >> 3) & 1) + (cta & 1));
    const uint32_t* zin = sc->z2 + (size_t)slot * 4800;
    if (wg == 2) {
      {
        uint4 v[4];
        const int i3 = min(t128 + 384, 431);
        int it = 0;
        while (true) {
          uint32_t bad = 0;
#pragma unroll
          for (int k = 0; k < 4; k++) v[k] = ld_rlx4(sc->mod + 2 * D_ + 4 * (k < 3 ? t128 + 128 * k : i3));
#pragma unroll
          for (int k = 0; k < 4; k++) {
            v[k].x ^= tag16; v[k].y ^= tag16; v[k].z ^= tag16; v[k].w ^= tag16;
            bad |= v[k].x | v[k].y | v[k].z | v[k].w;
          }
          if (!any(bad & 0xffffu) || ++it > SPIN_MAX) break;
        }
#pragma unroll
        for (int k = 0; k < 4; k++) sts4(sbase + O_MOD + 16 * (k < 3 ? t128 + 128 * k : i3), v[k].x, v[k].y, v[k].z, v[k].w);
      }
      CK(14);
      mbar_wait(full0 + 8 * B_Z2, 0);
      if (elect()) {
        load_a1(wp - 8, wp - 8);
        if (wp > 8 && wp - 8 < NG1) prefetch_l2(reinterpret_cast<const uint8_t*>(p.w1) + (size_t)(128 * (4 * ((wp - 8) >> 1) + (cta >> 5)) + 64 * (wp & 1) + 2 * (cta & 31)) * (2 * F_), 4 * F_);
      }
      __syncwarp();
    } else {
      uint32_t lo[9];
#pragma unroll
      for (int k1 = 0; k1 < 9; k1++) lo[k1] = pin(sbase + O_IN + line_off(k1, kap, 4 * wg + t, (cta >> 4) & 3));
      const uint32_t lx = pin(lo[0] + (kap ? 0 : 288 * 8));
      const uint32_t sb3 = pin(sbase + O_B3 + wg * 1024 + (l >> 4) * 2048 + (2 * (kap & 24) + (l & 15)) * 16);
      CK(14);
      if (wp == 0) {
        const uint32_t* zu = upin(zin);
        if (elect()) mbar_expect(full0 + 8 * B_Z2, 19200);
        wait_cnt(&sc->cnt[C_Z2], 120 * ep);
        if (elect()) {
          bulk_ld(sbase + O_IN, zu, 19200, full0 + 8 * B_Z2);
          TS(14);
        }
        __syncwarp();
      }
      mbar_wait(full0 + 8 * B_Z2, 0);
      CK(15);
      if (tid == 0) TS(11);
      uint2 v[10];
      uint32_t bad = 0;
#pragma unroll
      for (int k1 = 0; k1 < 10; k1++) v[k1] = lds2(k1 < 9 ? lo[k1] : lx);
#pragma unroll
      for (int k1 = 0; k1 < 10; k1 += 2) bad |= diff2(v[k1].x, v[k1 + 1].x, tag1);
      if (__builtin_expect(any(bad & 1), 0)) {
        FAILCNT(1);
        int it = 0;
        do {
          bad = 0;
#pragma unroll
          for (int k1 = 0; k1 < 10; k1++) v[k1] = ld_rlx2(reinterpret_cast<const uint8_t*>(zin) + ((k1 < 9 ? lo[k1] : lx) - (sbase + O_IN)));
#pragma unroll
          for (int k1 = 0; k1 < 10; k1 += 2) bad |= diff2(v[k1].x, v[k1 + 1].x, tag1);
        } while (any(bad & 1) && ++it < SPIN_MAX);
      }
      float2 za[9], zb[9];
#pragma unroll
      for (int i = 0; i < 9; i++) { za[i] = make_float2(bf_lo(v[i].x), bf_hi(v[i].x)); zb[i] = make_float2(bf_lo(v[i].y), bf_hi(v[i].y)); }
      if (kap == 0) {
#pragma unroll
        for (int k = 1; k < 5; k++) {
          float2 a = za[k], b = za[9 - k];
          za[k] = make_float2(a.x - b.y, a.y + b.x); za[9 - k] = make_float2(a.x + b.y, b.x - a.y);
          a = zb[k]; b = zb[9 - k];
          zb[k] = make_float2(a.x - b.y, a.y + b.x); zb[9 - k] = make_float2(a.x + b.y, b.x - a.y);
        }
        za[0].y = bf_lo(v[9].x); zb[0].y = bf_lo(v[9].y);
      }
      __syncwarp();
      dft9(za); dft9(zb);
#pragma unroll
      for (int n = 0; n < 8; n += 2) {
        const int i0 = (9 - n) % 9, i1 = 8 - n;
        stmatrix4(sb3 + n * 2048, pack_bf16(za[i0].x, zb[i0].x), pack_bf16(za[i0].y, zb[i0].y), pack_bf16(za[i1].x, zb[i1].x), pack_bf16(za[i1].y, zb[i1].y));
      }
      stmatrix2(sb3 + 8 * 2048, pack_bf16(za[1].x, zb[1].x), pack_bf16(za[1].y, zb[1].y));
      fence_async_smem();
    }
    CK(16);
    __syncthreads();
    CK(17);
    float acc[24];
    const uint32_t db = (((sbase + O_B3 + wg * 6144) & 0x3FFFF) >> 4) | ((128 >> 4) << 16);
    wg_fence();
#pragma unroll
    for (int kk = 0; kk < 4; kk++) wgmma_rs_48(acc, af[kk].x, af[kk].y, af[kk].z, af[kk].w, db + kk * 16, 1024 >> 4, kk);
    wg_commit();
    uint32_t ga[9];
    uint2 sh[9], sw[9];
    if (wg < 2) {
#pragma unroll
      for (int i = 0; i < 9; i++) {
        const uint2 v = lds2(sbase + O_MOD + (64 * i + 2 * l) * 4);
        ga[i] = __byte_perm(v.x, v.y, 0x7632);
        sh[i] = lds2(sbase + O_MOD + (D_ + 64 * i + 2 * l) * 4);
        sw[i] = lds2(sbase + O_MOD + (2 * D_ + 64 * i + 2 * l) * 4);
      }
    }
    wg_wait<0>();
    reg_fence(acc);
    CK(18);
#pragma unroll
    for (int i = 0; i < 3; i++) {
      const float* a = &acc[8 * i];
      const uint32_t a0 = pack_bf16(a[0], a[1]), a1 = pack_bf16(a[2], a[3]), a2 = pack_bf16(a[4], a[5]), a3 = pack_bf16(a[6], a[7]);
#pragma unroll
      for (int jh = 0; jh < 2; jh++) {
        float y[4];
        mma16<false>(y, a0, a1, a2, a3, tb[2 * jh], tb[2 * jh + 1]);
        sts(sy[2 * i] + jh * (4 * 584 * 4), pack_bf16(y[0], y[1]));
        sts(sy[2 * i + 1] + jh * (4 * 584 * 4), pack_bf16(y[2], y[3]));
      }
    }
    CK(19);
    if (wg == 2) bar_arrive(7, NTHR);
    else {
      bar_sync(7, NTHR);
      CK(20);
      float a[18], b[18];
#pragma unroll
      for (int i = 0; i < 9; i++) {
        const uint2 y = lds2(sbase + O_Y + (wp * 584 + 64 * i + 2 * l) * 4);
        xr[i] = hfma2(ga[i], __byte_perm(y.x, y.y, 0x5410), xr[i]);
        xr[9 + i] = hfma2(ga[i], __byte_perm(y.x, y.y, 0x7632), xr[9 + i]);
        a[2 * i] = bf_lo(xr[i]); a[2 * i + 1] = bf_hi(xr[i]); b[2 * i] = bf_lo(xr[9 + i]); b[2 * i + 1] = bf_hi(xr[9 + i]);
      }
      float oa, ra, ob, rb;
      ln_stats2(a, b, 1.0f, oa, ra, ob, rb);
      CK(21);
#pragma unroll
      for (int i = 0; i < 9; i++) {
        const float c0 = __uint_as_float(sw[i].x), c1 = __uint_as_float(sw[i].y), s0 = __uint_as_float(sh[i].x), s1 = __uint_as_float(sh[i].y);
        a[2 * i] = fmaf(fmaf(a[2 * i], ra, oa), c0, s0); a[2 * i + 1] = fmaf(fmaf(a[2 * i + 1], ra, oa), c1, s1);
        b[2 * i] = fmaf(fmaf(b[2 * i], rb, ob), c0, s0); b[2 * i + 1] = fmaf(fmaf(b[2 * i + 1], rb, ob), c1, s1);
      }
      ln_stats2(a, b, 0.5f, oa, ra, ob, rb);
      CK(22);
      const uint32_t sh3 = sbase + O_B3 + (wp >> 1) * 4608 + (l >> 4) * 256 + (wp & 1) * 128 + ((((l >> 2) ^ (2 * cta + (wp & 1))) & 3) << 4) + (l & 3) * 4;
#pragma unroll
      for (int i = 0; i < 9; i++) {
        sts(sh3 + i * 512, pack_bf16(fmaf(a[2 * i], ra, oa), fmaf(a[2 * i + 1], ra, oa)));
        sts(sh3 + i * 512 + 64, pack_bf16(fmaf(b[2 * i], rb, ob), fmaf(b[2 * i + 1], rb, ob)));
      }
      fence_async_smem();
      if (wp == 0) CKX(0);
      if (wp < 2 * H3G) bar_arrive(8, 32 + 64 * H3G); else bar_arrive(9, 288 - 64 * H3G);
      CK(23);
    }
  } else __syncthreads();

  const bool g2 = cta < 130 && (cta >> 1) != 56;
  const int z2 = cta < 112 ? cta : cta - 2, r = z2 >> 6;
  const int s2 = 128 * ((z2 >> 2) & 15), d2 = 144 * (z2 & 3);
  constexpr int XST = (33 + 36 - JSK - 1) % NST;
  constexpr int ST0 = (32 - JSK - 1) % NST, ST1 = 31 % NST;

  if (wg == 2) {
    asm volatile("setmaxnreg.dec.sync.aligned.u32 40;");
    if (wp == 8) {
      int st = rows ? 4 : 0, ph = 1;
#pragma unroll 1
      for (int kb = st; kb < 32; kb++) {
        if (rows && (kb >> 1) == 2) mbar_wait(full0 + 8 * (B_S4 - 4 + kb), 0);
        mbar_wait(empty0 + 8 * st, ph);
        if (elect()) {
          load_a1(st, kb);
          if (kb >= PF2K && kb < PF2K + PF2 && g2)
            prefetch_l2(reinterpret_cast<const uint8_t*>(p.w2) + (size_t)(36 * r + kb2_order(kb - PF2K)) * 262144 + (z2 & 63) * 4096, 4096);
        }
        __syncwarp();
        ring_next<false>(st, ph);
      }
      if (g2) {
        st++;
#pragma unroll 1
        for (int i = 0; i < 36; i++) {
          if (i == HOLDA) mbar_wait(full0 + 8 * B_GO, 0);
          mbar_wait(empty0 + 8 * st, ph);
          if (elect()) {
            mbar_expect(full0 + 8 * st, 16384 + 18432);
            tma3d_ef(sbase + st * STAGE, &maps.w2, 64 * (36 * r + kb2_order(i)), s2 >> 6, full0 + 8 * st);
          }
          __syncwarp();
          ring_next<true>(st, ph);
        }
      }
    } else if (wp >= 10) {
      const int sw = wp - 10;
      if (rows) {
        const CUtensorMap* mp = upin(&maps.h3[sw]);
        const uint32_t src = upin(sbase + O_B3 + sw * (H3G * 4608)), c0 = upin(64 * (cta & 15)), c1 = upin(18 * (cta >> 4)), c2 = upin(H3G * sw);
        unsigned* flag = pin(&sc->cnt[C_H3 + (cta >> 4) + 8 * sw]);
        bar_sync(8 + sw, sw ? 288 - 64 * H3G : 32 + 64 * H3G);
        if (!sw) CKX(1);
        if (sw) { mbar_wait(full0 + 8 * H3W, 0); CKX(7); }
        if (elect()) {
          tma_st3d(mp, src, c0, c1, c2);
          if (!sw) CKX(2);
          mbar_arrive(full0 + 8 * B_S4);
          bulk_commit_wait();
          if (!sw) CKX(3);
          mbar_arrive(full0 + 8 * B_S5);
          asm volatile("fence.acq_rel.gpu;" ::: "memory");
          red_add(flag, 1);
          if (!sw) CKX(4);
          TS(sw ? 24 : 13);
        }
        __syncwarp();
      }
      if (sw && g2) {
        mbar_wait(full0 + 8 * 5, 0);
#pragma unroll 1
        for (int i = 0; i < 36; i++) { sc->part[z2 * 1152 + 32 * i + l] = make_uint4(tag1 ^ 1, 0, 0, 0); __nanosleep(100); }
        __syncwarp();
      }
      const uint32_t stg = sbase + (sw ? ST1 : ST0) * STAGE;
      const int kbA = (f1 >> 6) + (helper ? 2 : 1) * (sw ^ flip), kbB = helper ? (f1 >> 6) + 1 : kbA;
      const int dB = helper ? d1 + 32 * sw : d1 + 96;
      uint8_t* const uA = upin(sc->u + ((size_t)kbA * D_ + d1) * 128);
      uint8_t* const uB = upin(sc->u + ((size_t)kbB * D_ + dB) * 128);
      unsigned* const fA = pin(&sc->cnt[C_U + kbA]);
      unsigned* const fB = pin(&sc->cnt[C_U + kbB]);
      bar_sync(11 + sw, 160);
      if (elect()) { bulk_st(uA, stg, 96 * 128); TS(sw ? 31 : 30); }
      __syncwarp();
      bar_sync(13 + sw, 160);
      if (elect()) {
        bulk_st(uB, stg + 96 * 128, helper ? 32 * 128 : 64 * 128);
        if (helper) bulk_st(uB + (64 - 16 * sw) * 128, stg + 128 * 128, 16 * 128);
        bulk_commit_wait();
        mbar_arrive(empty0 + 8 * (sw ? ST1 : ST0));
        if (sw == 0) TS(26);
        asm volatile("fence.acq_rel.gpu;" ::: "memory");
        red_add(fA, 2);
        if (helper) red_add(fB, 1);
        TS(sw ? 23 : 17);
      }
      __syncwarp();
    } else {
      uint64_t ready = 0;
      int st = 0, ph = 1;
#pragma unroll 1
      for (int kb = 0; kb < 32; kb++) {
        const uint8_t* src = upin(sc->h3 + ((size_t)(kb * 18 + (d1 >> 5)) << 12));
        const uint32_t dst = upin(sbase + st * STAGE + a1bytes);
        if (rows && (kb >> 1) == 2) mbar_wait(full0 + 8 * (B_S4 - 4 + kb), 0);
        mbar_wait(empty0 + 8 * st, ph);
        wait_flags(sc->cnt + C_H3, 32, (kb & 7) + (kb < 8 * H3G ? 0 : 8), 16 * ep, ready);
        if (kb == 0) CKX(5);
        if (elect()) bulk_ld(dst, src, STAGE - a1bytes, full0 + 8 * st);
        if (kb == 0) CKX(6);
        if (kb == 5) CKX(8);
        if (kb == 8 * H3G) CKX(9);
        ring_next<false>(st, ph);
      }
      if (g2) {
        ready = 0;
        st++;
#pragma unroll 1
        for (int i = 0; i < 72; i++) {
          if (i == 36) ready = 0;
          const int kb = kb2_order(i < 36 ? i : i - 36), hf = r ^ (i >= 36);
          const uint8_t* src = upin(sc->u + ((size_t)(36 * r + kb) * D_ + d2) * 128);
          const uint32_t dst = upin(sbase + st * STAGE + 16384);
          if (i <= 36) mbar_wait(empty0 + 8 * st, ph);
          wait_flags(sc->cnt + C_U + 36 * hf, 36, kb, 8 * ep, ready);
          if (i < 36) {
            if (elect()) {
              bulk_ld(dst, src, 18432, full0 + 8 * st);
              if (i == GOAT) mbar_arrive(full0 + 8 * B_GO);
            }
            ring_next<true>(st, ph);
          } else if (ready == ~0ull) break;
        }
        if (l == 0) mbar_expect(full0 + 8 * XST, 18432);
        __syncwarp();
        if (l < 3) tma2d(sbase + XST * STAGE + 18432 + l * 6144, &maps.x1, d2 + 48 * l, s2 + 64 * (r ^ 1), full0 + 8 * XST);
        __syncwarp();
      }
    }
  } else {
    asm volatile("setmaxnreg.inc.sync.aligned.u32 232;");
    const int wgu = wg;
    constexpr uint32_t sb4 = sbase >> 4;
    const int w = wp & 3;
    Ring rg = {0, 0};
    uint32_t* const x1p = sc->x1 + (size_t)(cta + 256 * wp) * 288 + l;
    float acc[80];
    constexpr uint32_t LA = (8192 >> 4) << 16, LB = (4096 >> 4) << 16;
    {
      const int fa = f1 + (helper ? 128 : 64) * (wg ^ flip) + 16 * w + g, fb = helper ? f1 + 64 + 16 * w + g : fa;
      const float a0 = 0.5f * __bfloat162float(p.b1[fa]), a1 = 0.5f * __bfloat162float(p.b1[fa + 8]);
      const float b0 = 0.5f * __bfloat162float(p.b1[fb]), b1 = 0.5f * __bfloat162float(p.b1[fb + 8]);
#pragma unroll
      for (int i = 0; i < 80; i++) acc[i] = i < 48 ? ((i & 2) ? a1 : a0) : ((i & 2) ? b1 : b0);
      reg_fence(acc);
    }
    if (!helper) gemm_main<0>(acc, sb4 + (wgu ^ flip) * 512 + LA, 0, sb4 + 1024 + LB, 0, wgu, rg, x1p, xr);
    else {
      float ac2[80];
#pragma unroll
      for (int i = 0; i < 72; i++) asm volatile("mov.b32 %0, %1;" : "=f"(ac2[i]) : "f"(acc[i]));
      gemm_main<1>(ac2, sb4 + (wgu ^ flip) * 1024 + LA, sb4 + 512 + LA, sb4 + 1536 + LB, sb4 + 1536 + (wgu ? 256 + LB + (2 << 16) : 2 * LB), wgu, rg, x1p, xr);
#pragma unroll
      for (int i = 0; i < 72; i++) asm volatile("mov.b32 %0, %1;" : "=f"(acc[i]) : "f"(ac2[i]));
    }
    if (t128 == 0) TS(wg ? 16 : 6);
    {
      const int mi = l >> 3, rr = l & 7;
      const uint32_t ad = sbase + (wg ? ST1 : ST0) * STAGE + (8 * (mi >> 1) + rr) * 128 + (((2 * w + (mi & 1)) ^ rr) << 4);
      float z[2][16];
#pragma unroll
      for (int j = -1; j <= 5; j++) {
        if (j >= 1) {
          const float* a = &acc[16 * (j - 1)];
          const float* tt = z[(j - 1) & 1];
#pragma unroll
          for (int h = 0; h < 16; h += 8)
            stmatrix4t(ad + (2 * (j - 1) + (h >> 3)) * 2048, pack_bf16(fmaf(a[h], tt[h], a[h]), fmaf(a[h + 1], tt[h + 1], a[h + 1])),
                       pack_bf16(fmaf(a[h + 2], tt[h + 2], a[h + 2]), fmaf(a[h + 3], tt[h + 3], a[h + 3])),
                       pack_bf16(fmaf(a[h + 4], tt[h + 4], a[h + 4]), fmaf(a[h + 5], tt[h + 5], a[h + 5])),
                       pack_bf16(fmaf(a[h + 6], tt[h + 6], a[h + 6]), fmaf(a[h + 7], tt[h + 7], a[h + 7])));
        }
        if (j >= 0 && j < 5) {
#pragma unroll
          for (int e = 0; e < 16; e++) asm("tanh.approx.f32 %0, %0;" : "+f"(z[j & 1][e]));
        }
        if (j < 4) {
#pragma unroll
          for (int e = 0; e < 16; e++) z[(j + 1) & 1][e] = gelu_arg(acc[16 * (j + 1) + e]);
        }
        if (j == 3 || j == 5) { fence_async_smem(); asm volatile("bar.arrive %0, 160;" ::"r"((j == 3 ? 11 : 13) + wgu) : "memory"); }
        if (j < 5) {
          if (j >= 0) reg_fence(z[j & 1]);
          if (j < 4) reg_fence(z[(j + 1) & 1]);
          if (__builtin_expect(wp == 0x7ffffff0 + j, 0)) __trap();
          reg_fence(acc);
        }
      }
      if (t128 == 0) TS(wg ? 29 : 28);
    }
    if (g2) {
      const int mb = wgu ^ r;
      uint32_t gb[18];
      {
        float a0 = 0.f, a1 = 0.f;
        if (wgu) {
          a0 = __bfloat162float(p.b2[s2 + 64 * mb + 16 * w + g]); a1 = __bfloat162float(p.b2[s2 + 64 * mb + 16 * w + 8 + g]);
          int it = 0;
          uint32_t bad;
          do {
            bad = 0;
#pragma unroll
            for (int i = 0; i < 18; i++) {
              const uint2 v = ld_rlx2(sc->mod + 5 * D_ + d2 + 8 * i + 2 * t);
              bad |= (v.x ^ tag16) | (v.y ^ tag16);
              gb[i] = __byte_perm(v.x, v.y, 0x7632);
            }
          } while (any(bad & 0xffffu) && ++it < SPIN_MAX);
        }
#pragma unroll
        for (int i = 0; i < 72; i++) acc[i] = (i & 2) ? a1 : a0;
      }
      rg.st++;
      gemm_main<3>(acc, sb4 + mb * 512 + LA, 0, sb4 + 1024 + (1 << 16), 0, wgu, rg, x1p, xr);
      if (t128 == 0) TS(wg ? 20 : 19);
      const uint32_t sx = sbase + XST * STAGE;
      if (wgu == 0) {
        uint4* dst = sc->part + z2 * 1152 + t128;
#pragma unroll
        for (int j = 0; j < 9; j++) {
          const float* a = &acc[8 * j];
          dst[j * 128] = make_uint4(set_tag(pack_bf16(a[0], a[1]), tag1), pack_bf16(a[2], a[3]), pack_bf16(a[4], a[5]), pack_bf16(a[6], a[7]));
        }
        if (tid == 0) TS(21);
        const uint4* src = sc->part + (z2 ^ 64) * 1152 + t128;
        uint4 v[9];
        uint32_t bad;
        int it = 0;
        do {
#pragma unroll
          for (int j = 0; j < 9; j++) v[j] = ld_rlx4(src + j * 128);
          bad = v[8].x ^ tag1;
#pragma unroll
          for (int j = 0; j < 8; j += 2) bad |= diff2(v[j].x, v[j + 1].x, tag1);
        } while (any(bad & 1) && ++it < SPIN_MAX);
#pragma unroll
        for (int j = 0; j < 9; j++) sts4(sx + t128 * 16 + j * 2048, v[j].x, v[j].y, v[j].z, v[j].w);
        bar_arrive(2 + w, 64);
        if (w == 0) {
#pragma unroll 1
          for (int i = 0; i < 3; i++) {
            bar_sync(11 + i, 160);
            if (elect()) tma_st2d(&maps.out, sx + 18432 + i * 6144, d2 + 48 * i, s2 + 64 * (r ^ 1));
            __syncwarp();
          }
          if (elect()) { bulk_commit_wait_read(); TS(22); }
          __syncwarp();
        }
      } else {
        mbar_wait(full0 + 8 * XST, rg.ph);
        bar_sync(2 + w, 64);
        if (t128 == 0) TS(5);
        if (tid == 128 && cta == 0) sc->cnt[C_EP] = ep;
        const uint32_t xa = sx + 18432 + (16 * w + (l & 15)) * 96 + (l >> 4) * 16;
#pragma unroll
        for (int c = 0; c < 3; c++) {
          uint32_t pv[3][4], xv[3][4];
#pragma unroll
          for (int j = 0; j < 3; j++) {
            asm volatile("ld.shared.v4.b32 {%0,%1,%2,%3}, [%4];" : "=r"(pv[j][0]), "=r"(pv[j][1]), "=r"(pv[j][2]), "=r"(pv[j][3]) : "r"(sx + t128 * 16 + (3 * c + j) * 2048) : "memory");
            asm volatile("ldmatrix.sync.aligned.m8n8.x4.shared.b16 {%0,%1,%2,%3}, [%4];" : "=r"(xv[j][0]), "=r"(xv[j][1]), "=r"(xv[j][2]), "=r"(xv[j][3]) : "r"(xa + c * 6144 + j * 32) : "memory");
          }
#pragma unroll
          for (int j = 0; j < 3; j++) {
            const float* a = &acc[8 * (3 * c + j)];
            uint32_t o[4];
#pragma unroll
            for (int e = 0; e < 4; e++)
              o[e] = hadd2(xv[j][e], hmul2(gb[2 * (3 * c + j) + (e >> 1)], pack_bf16(a[2 * e] + bf_lo(pv[j][e]), a[2 * e + 1] + bf_hi(pv[j][e]))));
            stmatrix4(xa + c * 6144 + j * 32, o[0], o[1], o[2], o[3]);
          }
          fence_async_smem();
          asm volatile("bar.arrive %0, 160;" ::"r"(11 + c) : "memory");
        }
        if (t128 == 0) TS(7);
        __syncwarp();
      }
    }
  }
}

typedef CUresult (*EncodeFn)(CUtensorMap*, CUtensorMapDataType, cuuint32_t, void*, const cuuint64_t*, const cuuint64_t*, const cuuint32_t*,
                             const cuuint32_t*, CUtensorMapInterleave, CUtensorMapSwizzle, CUtensorMapL2promotion, CUtensorMapFloatOOBfill);

struct Dim { cuuint64_t n, stride; cuuint32_t box; };
template <int RANK>
void make_map(EncodeFn enc, CUtensorMap* m, bool words, int swz, const void* ptr, const Dim (&d)[RANK]) {
  cuuint64_t gd[RANK], gs[RANK];
  cuuint32_t bx[RANK], es[RANK];
  for (int i = 0; i < RANK; i++) { gd[i] = d[i].n; gs[i] = d[i].stride; bx[i] = d[i].box; es[i] = 1; }
  enc(m, words ? CU_TENSOR_MAP_DATA_TYPE_UINT32 : CU_TENSOR_MAP_DATA_TYPE_BFLOAT16, RANK, const_cast<void*>(ptr), gd, gs + 1, bx, es,
      CU_TENSOR_MAP_INTERLEAVE_NONE, static_cast<CUtensorMapSwizzle>(swz),
      swz == 3 ? CU_TENSOR_MAP_L2_PROMOTION_L2_256B : CU_TENSOR_MAP_L2_PROMOTION_NONE, CU_TENSOR_MAP_FLOAT_OOB_FILL_NONE);
}

}

extern "C" void kernel_launch(void* const* d_in, const int* in_sizes, int n_in, void* d_out, int out_size) {
  (void)in_sizes; (void)n_in; (void)out_size;
  static EncodeFn enc = nullptr;
  static void *sptr = nullptr, *tptr = nullptr;
  if (!enc) {
    void* f = nullptr; cudaDriverEntryPointQueryResult qr;
    cudaGetDriverEntryPoint("cuTensorMapEncodeTiled", &f, cudaEnableDefault, &qr);
    enc = reinterpret_cast<EncodeFn>(f);
    cudaFuncSetAttribute(fused_kernel, cudaFuncAttributeMaxDynamicSharedMemorySize, SMEM_BYTES);
    cudaGetSymbolAddress(&sptr, g_s);
    cudaGetSymbolAddress(&tptr, T_TAB);
  }
  Params p;
  p.x = (const __nv_bfloat16*)d_in[0]; p.wr = (const __nv_bfloat16*)d_in[1]; p.wi = (const __nv_bfloat16*)d_in[2];
  p.b1 = (const __nv_bfloat16*)d_in[5]; p.b2 = (const __nv_bfloat16*)d_in[7];
  p.c = (const __nv_bfloat16*)d_in[8]; p.wmod = (const __nv_bfloat16*)d_in[9];
  p.w1 = (const __nv_bfloat16*)d_in[4]; p.w2 = (const __nv_bfloat16*)d_in[6];
  p.s = static_cast<Scratch*>(sptr); p.tab = static_cast<const uint4*>(tptr);
  Maps maps;
  make_map<4>(enc, &maps.w1a, false, 3, p.w1, {{64, 0, 64}, {16, 128 * 2 * F_, 4}, {128, 2 * F_, 16}, {72, 128, 2}});
  make_map<4>(enc, &maps.w1b, false, 3, p.w1, {{64, 0, 64}, {16, 128 * 2 * F_, 4}, {128, 2 * F_, 16}, {72, 128, 3}});
  make_map<3>(enc, &maps.w2, false, 3, p.w2, {{64, 0, 64}, {F_, 2 * S_, 64}, {32, 128, 2}});
  make_map<2>(enc, &maps.x1, false, 0, p.s->x1, {{D_, 0, 48}, {S_, 2 * D_, 64}});
  make_map<2>(enc, &maps.out, false, 0, d_out, {{D_, 0, 48}, {S_, 2 * D_, 64}});
  make_map<2>(enc, &maps.z1, true, 0, p.s->z1, {{5120, 0, 40}, {120, 20480, 60}});
  make_map<2>(enc, &maps.z2, true, 0, p.s->z2, {{4800, 0, 40}, {128, 19200, 128}});
  for (int i = 0; i < 4; i++) make_map<2>(enc, &maps.wf[i], false, 2 - (i & 1), (i & 2) ? p.wi : p.wr, {{16 * DF_, 0, (i & 1) ? 16u : 32u}, {128, 32 * DF_, 128}});
  make_map<2>(enc, &maps.wm, false, 0, p.wmod, {{6 * D_, 0, 16}, {D_, 12 * D_, 192}});
  for (int i = 0; i < 2; i++) make_map<3>(enc, &maps.h3[i], true, 0, p.s->h3, {{1024, 0, 64}, {144, 4096, 18}, {4, 144 * 4096, i ? 4u - H3G : H3G}});
  fused_kernel<<<NCTA, NTHR, SMEM_BYTES, cudaStreamPerThread>>>(p, maps);
}
```

```cpp
#include <cuda_runtime.h>
#include <cuda_bf16.h>
#include <cuda.h>
#include <stdint.h>

namespace {

constexpr int S_ = 2048, D_ = 576, DF_ = 289, F_ = 4608;
constexpr int NCTA = 132, NTHR = 384;
constexpr int STAGE = 36864, NST = 6;
constexpr uint32_t sbase = 1024, full0 = sbase + NST * STAGE, empty0 = full0 + 8 * NST, red = full0 + 256;
constexpr int SMEM_BYTES = NST * STAGE + 256 + 512 + 4 * D_ + 512;
constexpr int O_NRM = 0, O_B1 = 19456, O_Z1 = 38912, O_P2 = 59392;
constexpr int O_RAW = 4 * STAGE;
constexpr int O_IN = 4 * STAGE, O_Y = O_IN + 19456, O_B3 = O_IN + 38912, O_MOD = O_IN + 57344;

__device__ __align__(128) const uint32_t T_TAB[5632] = {
0x3f803f80,0xbf803f80,0x3f803f80,0xbf803f80,0x3f803f80,0xbf803f80,0x3f803f80,0xbf803f80,0x3f803f80,0xbf803f80,0x3f803f80,0xbf803f80,
0x3f803f80,0xbf803f80,0x3f803f80,0xbf803f80,0x3f7f3f80,0xbdc90000,0x3f223f35,0xbf46bf35,0x3f753f7b,0xbe95be48,0x3ef13f0e,0xbf62bf55,
0x3f623f6d,0xbef1bec4,0x3e953ec4,0xbf75bf6d,0x3f463f55,0xbf22bf0e,0x3dc93e48,0xbf7fbf7b,0x3f7b3f80,0xbe480000,0xbe480000,0xbf7bbf80,
0x3f553f6d,0xbf0ebec4,0xbf0ebec4,0xbf55bf6d,0x3f0e3f35,0xbf55bf35,0xbf55bf35,0xbf0ebf35,0x3e483ec4,0xbf7bbf6d,0xbf7bbf6d,0xbe48bec4,
0x3f753f80,0xbe950000,0xbf62bf35,0xbef1bf35,0x3f223f55,0xbf46bf0e,0xbf7fbf7b,0x3dc9be48,0x3dc93ec4,0xbf7fbf6d,0xbf46bf6d,0x3f223ec4,
0xbef1be48,0xbf62bf7b,0xbe95bf0e,0x3f753f55,0x3f6d3f80,0xbec40000,0xbf6dbf80,0x3ec40000,0x3ec43f35,0xbf6dbf35,0xbec4bf35,0x3f6d3f35,
0xbec40000,0xbf6dbf80,0x3ec40000,0x3f6d3f80,0xbf6dbf35,0xbec4bf35,0x3f6d3f35,0x3ec43f35,0x3f623f80,0xbef10000,0xbe95bf35,0x3f753f35,
0x3dc93f0e,0xbf7fbf55,0x3f223e48,0x3f463f7b,0xbf46bec4,0xbf22bf6d,0x3f7f3f6d,0xbdc93ec4,0xbf75bf7b,0x3e95be48,0x3ef13f55,0xbf62bf0e,
0x3f553f80,0xbf0e0000,0x3f0e0000,0x3f553f80,0xbe483ec4,0xbf7bbf6d,0x3f7b3f6d,0xbe483ec4,0xbf7bbf35,0xbe48bf35,0x3e483f35,0xbf7bbf35,
0xbf0ebf6d,0x3f553ec4,0xbf55bec4,0xbf0ebf6d,0x3f463f80,0xbf220000,0x3f7f3f35,0x3dc93f35,0xbef13e48,0xbf62bf7b,0x3e953f55,0xbf75bf0e,
0xbf75bf6d,0x3e95bec4,0xbf62bec4,0xbef1bf6d,0x3dc9bf0e,0x3f7f3f55,0xbf22bf7b,0x3f463e48,0x3f353f80,0xbf350000,0x3f353f80,0xbf350000,
0xbf350000,0xbf35bf80,0xbf350000,0xbf35bf80,0xbf35bf80,0x3f350000,0xbf35bf80,0x3f350000,0x3f350000,0x3f353f80,0x3f350000,0x3f353f80,
0x3f223f80,0xbf460000,0xbdc93f35,0xbf7fbf35,0xbf62be48,0xbef1bf7b,0xbf75bf55,0x3e95bf0e,0xbe95bf6d,0x3f753ec4,0x3ef1bec4,0x3f623f6d,
0x3f7f3f0e,0x3dc93f55,0x3f463f7b,0xbf223e48,0x3f0e3f80,0xbf550000,0xbf550000,0xbf0ebf80,0xbf7bbec4,0xbe48bf6d,0xbe48bf6d,0x3f7b3ec4,
0x3e48bf35,0x3f7b3f35,0x3f7b3f35,0xbe483f35,0x3f553f6d,0xbf0e3ec4,0xbf0e3ec4,0xbf55bf6d,0x3ef13f80,0xbf620000,0xbf75bf35,0x3e95bf35,
0xbf7fbf0e,0x3dc9bf55,0x3f46be48,0x3f223f7b,0x3f22bec4,0x3f463f6d,0x3dc93f6d,0xbf7fbec4,0x3e953f7b,0xbf75be48,0xbf62bf55,0x3ef1bf0e,
0x3ec43f80,0xbf6d0000,0xbec4bf80,0x3f6d0000,0xbf6dbf35,0x3ec4bf35,0x3f6d3f35,0xbec43f35,0x3f6d0000,0x3ec43f80,0xbf6d0000,0xbec4bf80,
0xbec43f35,0xbf6dbf35,0x3ec4bf35,0x3f6d3f35,0x3e953f80,0xbf750000,0x3ef1bf35,0x3f623f35,0xbf46bf55,0x3f22bf0e,0x3dc93f7b,0xbf7fbe48,
0x3f7f3ec4,0xbdc93f6d,0xbf22bf6d,0x3f46bec4,0xbf623e48,0xbef1bf7b,0x3f753f0e,0xbe953f55,0x3e483f80,0xbf7b0000,0x3f7b0000,0x3e483f80,
0xbf0ebf6d,0x3f55bec4,0xbf553ec4,0xbf0ebf6d,0x3f553f35,0xbf0e3f35,0x3f0ebf35,0x3f553f35,0xbf7bbec4,0x3e48bf6d,0xbe483f6d,0xbf7bbec4,
0x3dc93f80,0xbf7f0000,0x3f463f35,0xbf223f35,0xbe95bf7b,0x3f75be48,0xbf62bf0e,0x3ef1bf55,0x3ef13f6d,0xbf623ec4,0x3f753ec4,0xbe953f6d,
0xbf22bf55,0x3f46bf0e,0xbf7fbe48,0x3dc9bf7b,0x3f80,0xbf800000,0x3f80,0xbf800000,0xbf80,0x3f800000,0xbf80,0x3f800000,
0x3f80,0xbf800000,0x3f80,0xbf800000,0xbf80,0x3f800000,0xbf80,0x3f800000,0xbdc93f80,0xbf7f0000,0xbf463f35,0xbf22bf35,
0x3e95bf7b,0x3f753e48,0x3f62bf0e,0x3ef13f55,0xbef13f6d,0xbf62bec4,0xbf753ec4,0xbe95bf6d,0x3f22bf55,0x3f463f0e,0x3f7fbe48,0x3dc93f7b,
0xbe483f80,0xbf7b0000,0xbf7b0000,0x3e48bf80,0x3f0ebf6d,0x3f553ec4,0x3f553ec4,0xbf0e3f6d,0xbf553f35,0xbf0ebf35,0xbf0ebf35,0x3f55bf35,
0x3f7bbec4,0x3e483f6d,0x3e483f6d,0xbf7b3ec4,0xbe953f80,0xbf750000,0xbef1bf35,0x3f62bf35,0x3f46bf55,0x3f223f0e,0xbdc93f7b,0xbf7f3e48,
0xbf7f3ec4,0xbdc9bf6d,0x3f22bf6d,0x3f463ec4,0x3f623e48,0xbef13f7b,0xbf753f0e,0xbe95bf55,0xbec43f80,0xbf6d0000,0x3ec4bf80,0x3f6d0000,
0x3f6dbf35,0x3ec43f35,0xbf6d3f35,0xbec4bf35,0xbf6d0000,0x3ec4bf80,0x3f6d0000,0xbec43f80,0x3ec43f35,0xbf6d3f35,0xbec4bf35,0x3f6dbf35,
0xbef13f80,0xbf620000,0x3f75bf35,0x3e953f35,0x3f7fbf0e,0x3dc93f55,0xbf46be48,0x3f22bf7b,0xbf22bec4,0x3f46bf6d,0xbdc93f6d,0xbf7f3ec4,
0xbe953f7b,0xbf753e48,0x3f62bf55,0x3ef13f0e,0xbf0e3f80,0xbf550000,0x3f550000,0xbf0e3f80,0x3f7bbec4,0xbe483f6d,0x3e48bf6d,0x3f7bbec4,
0xbe48bf35,0x3f7bbf35,0xbf7b3f35,0xbe48bf35,0xbf553f6d,0xbf0ebec4,0x3f0e3ec4,0xbf553f6d,0xbf223f80,0xbf460000,0x3dc93f35,0xbf7f3f35,
0x3f62be48,0xbef13f7b,0x3f75bf55,0x3e953f0e,0x3e95bf6d,0x3f75bec4,0xbef1bec4,0x3f62bf6d,0xbf7f3f0e,0x3dc9bf55,0xbf463f7b,0xbf22be48,
0xbf353f80,0xbf350000,0xbf353f80,0xbf350000,0x3f350000,0xbf353f80,0x3f350000,0xbf353f80,0x3f35bf80,0x3f350000,0x3f35bf80,0x3f350000,
0xbf350000,0x3f35bf80,0xbf350000,0x3f35bf80,0xbf463f80,0xbf220000,0xbf7f3f35,0x3dc9bf35,0x3ef13e48,0xbf623f7b,0xbe953f55,0xbf753f0e,
0x3f75bf6d,0x3e953ec4,0x3f62bec4,0xbef13f6d,0xbdc9bf0e,0x3f7fbf55,0x3f22bf7b,0x3f46be48,0xbf553f80,0xbf0e0000,0xbf0e0000,0x3f55bf80,
0x3e483ec4,0xbf7b3f6d,0xbf7b3f6d,0xbe48bec4,0x3f7bbf35,0xbe483f35,0xbe483f35,0xbf7b3f35,0x3f0ebf6d,0x3f55bec4,0x3f55bec4,0xbf0e3f6d,
0xbf623f80,0xbef10000,0x3e95bf35,0x3f75bf35,0xbdc93f0e,0xbf7f3f55,0xbf223e48,0x3f46bf7b,0x3f46bec4,0xbf223f6d,0xbf7f3f6d,0xbdc9bec4,
0x3f75bf7b,0x3e953e48,0xbef13f55,0xbf623f0e,0xbf6d3f80,0xbec40000,0x3f6dbf80,0x3ec40000,0xbec43f35,0xbf6d3f35,0x3ec4bf35,0x3f6dbf35,
0x3ec40000,0xbf6d3f80,0xbec40000,0x3f6dbf80,0x3f6dbf35,0xbec43f35,0xbf6d3f35,0x3ec4bf35,0xbf753f80,0xbe950000,0x3f62bf35,0xbef13f35,
0xbf223f55,0xbf463f0e,0x3f7fbf7b,0x3dc93e48,0xbdc93ec4,0xbf7f3f6d,0x3f46bf6d,0x3f22bec4,0x3ef1be48,0xbf623f7b,0x3e95bf0e,0x3f75bf55,
0xbf7b3f80,0xbe480000,0x3e480000,0xbf7b3f80,0xbf553f6d,0xbf0e3ec4,0x3f0ebec4,0xbf553f6d,0xbf0e3f35,0xbf553f35,0x3f55bf35,0xbf0e3f35,
0xbe483ec4,0xbf7b3f6d,0x3f7bbf6d,0xbe483ec4,0xbf7f3f80,0xbdc90000,0xbf223f35,0xbf463f35,0xbf753f7b,0xbe953e48,0xbef13f0e,0xbf623f55,
0xbf623f6d,0xbef13ec4,0xbe953ec4,0xbf753f6d,0xbf463f55,0xbf223f0e,0xbdc93e48,0xbf7f3f7b,0x3f803f80,0xbf803f80,0x3f803f80,0xbf803f80,
0x3f803f80,0xbf803f80,0x3f803f80,0xbf803f80,0x3f803f80,0xbf803f80,0x3f803f80,0xbf803f80,0x3f803f80,0xbf803f80,0x3f803f80,0xbf803f80,
0xbdc90000,0xbf7fbf80,0xbf46bf35,0xbf22bf35,0xbe95be48,0xbf75bf7b,0xbf62bf55,0xbef1bf0e,0xbef1bec4,0xbf62bf6d,0xbf75bf6d,0xbe95bec4,
0xbf22bf0e,0xbf46bf55,0xbf7fbf7b,0xbdc9be48,0xbf7bbf80,0x3e480000,0x3e480000,0x3f7b3f80,0xbf55bf6d,0x3f0e3ec4,0x3f0e3ec4,0x3f553f6d,
0xbf0ebf35,0x3f553f35,0x3f553f35,0x3f0e3f35,0xbe48bec4,0x3f7b3f6d,0x3f7b3f6d,0x3e483ec4,0x3e950000,0x3f753f80,0x3ef13f35,0xbf62bf35,
0x3f463f0e,0x3f223f55,0xbdc93e48,0xbf7fbf7b,0x3f7f3f6d,0x3dc93ec4,0xbf22bec4,0xbf46bf6d,0x3f623f7b,0xbef1be48,0xbf75bf55,0xbe95bf0e,
0x3f6d3f80,0xbec40000,0xbf6dbf80,0x3ec40000,0x3ec43f35,0xbf6dbf35,0xbec4bf35,0x3f6d3f35,0xbec40000,0xbf6dbf80,0x3ec40000,0x3f6d3f80,
0xbf6dbf35,0xbec4bf35,0x3f6d3f35,0x3ec43f35,0xbef10000,0xbf62bf80,0x3f753f35,0x3e953f35,0xbf7fbf55,0xbdc9bf0e,0x3f463f7b,0xbf22be48,
0xbf22bf6d,0x3f463ec4,0xbdc93ec4,0xbf7fbf6d,0x3e95be48,0x3f753f7b,0xbf62bf0e,0xbef1bf55,0xbf55bf80,0x3f0e0000,0xbf0e0000,0xbf55bf80,
0x3e48bec4,0x3f7b3f6d,0xbf7bbf6d,0x3e48bec4,0x3f7b3f35,0x3e483f35,0xbe48bf35,0x3f7b3f35,0x3f0e3f6d,0xbf55bec4,0x3f553ec4,0x3f0e3f6d,
0x3f220000,0x3f463f80,0xbdc9bf35,0x3f7f3f35,0x3f623f7b,0xbef13e48,0x3f753f0e,0x3e953f55,0xbe953ec4,0xbf75bf6d,0x3ef13f6d,0xbf62bec4,
0xbf7fbf55,0x3dc9bf0e,0xbf46be48,0xbf22bf7b,0x3f353f80,0xbf350000,0x3f353f80,0xbf350000,0xbf350000,0xbf35bf80,0xbf350000,0xbf35bf80,
0xbf35bf80,0x3f350000,0xbf35bf80,0x3f350000,0x3f350000,0x3f353f80,0x3f350000,0x3f353f80,0xbf460000,0xbf22bf80,0xbf7fbf35,0x3dc9bf35,
0xbef1bf7b,0x3f623e48,0x3e95bf0e,0x3f753f55,0x3f753ec4,0x3e953f6d,0x3f623f6d,0xbef13ec4,0x3dc93f55,0xbf7fbf0e,0xbf223e48,0xbf46bf7b,
0xbf0ebf80,0x3f550000,0x3f550000,0x3f0e3f80,0x3f7b3ec4,0x3e483f6d,0x3e483f6d,0xbf7bbec4,0xbe483f35,0xbf7bbf35,0xbf7bbf35,0x3e48bf35,
0xbf55bf6d,0x3f0ebec4,0x3f0ebec4,0x3f553f6d,0x3f620000,0x3ef13f80,0xbe953f35,0xbf75bf35,0xbdc93f55,0xbf7fbf0e,0xbf22bf7b,0x3f46be48,
0xbf46bf6d,0x3f22bec4,0x3f7f3ec4,0x3dc93f6d,0x3f753e48,0x3e953f7b,0xbef13f0e,0xbf62bf55,0x3ec43f80,0xbf6d0000,0xbec4bf80,0x3f6d0000,
0xbf6dbf35,0x3ec4bf35,0x3f6d3f35,0xbec43f35,0x3f6d0000,0x3ec43f80,0xbf6d0000,0xbec4bf80,0xbec43f35,0xbf6dbf35,0x3ec4bf35,0x3f6d3f35,
0xbf750000,0xbe95bf80,0x3f623f35,0xbef13f35,0x3f22bf0e,0x3f463f55,0xbf7fbe48,0xbdc9bf7b,0xbdc93f6d,0xbf7fbec4,0x3f46bec4,0x3f223f6d,
0xbef1bf7b,0x3f62be48,0xbe953f55,0xbf75bf0e,0xbe48bf80,0x3f7b0000,0xbf7b0000,0xbe48bf80,0x3f0e3f6d,0xbf553ec4,0x3f55bec4,0x3f0e3f6d,
0xbf55bf35,0x3f0ebf35,0xbf0e3f35,0xbf55bf35,0x3f7b3ec4,0xbe483f6d,0x3e48bf6d,0x3f7b3ec4,0x3f7f0000,0x3dc93f80,0x3f22bf35,0x3f463f35,
0xbf753e48,0xbe95bf7b,0xbef13f55,0xbf62bf0e,0x3f62bec4,0x3ef13f6d,0x3e95bf6d,0x3f753ec4,0xbf463f0e,0xbf22bf55,0xbdc93f7b,0xbf7fbe48,
0x3f80,0xbf800000,0x3f80,0xbf800000,0xbf80,0x3f800000,0xbf80,0x3f800000,0x3f80,0xbf800000,0x3f80,0xbf800000,
0xbf80,0x3f800000,0xbf80,0x3f800000,0xbf7f0000,0x3dc9bf80,0xbf22bf35,0x3f46bf35,0x3f753e48,0xbe953f7b,0x3ef13f55,0xbf623f0e,
0xbf62bec4,0x3ef1bf6d,0xbe95bf6d,0x3f75bec4,0x3f463f0e,0xbf223f55,0x3dc93f7b,0xbf7f3e48,0x3e48bf80,0x3f7b0000,0x3f7b0000,0xbe483f80,
0xbf0e3f6d,0xbf55bec4,0xbf55bec4,0x3f0ebf6d,0x3f55bf35,0x3f0e3f35,0x3f0e3f35,0xbf553f35,0xbf7b3ec4,0xbe48bf6d,0xbe48bf6d,0x3f7bbec4,
0x3f750000,0xbe953f80,0xbf623f35,0xbef1bf35,0xbf22bf0e,0x3f46bf55,0x3f7fbe48,0xbdc93f7b,0x3dc93f6d,0xbf7f3ec4,0xbf46bec4,0x3f22bf6d,
0x3ef1bf7b,0x3f623e48,0x3e953f55,0xbf753f0e,0xbec43f80,0xbf6d0000,0x3ec4bf80,0x3f6d0000,0x3f6dbf35,0x3ec43f35,0xbf6d3f35,0xbec4bf35,
0xbf6d0000,0x3ec4bf80,0x3f6d0000,0xbec43f80,0x3ec43f35,0xbf6d3f35,0xbec4bf35,0x3f6dbf35,0xbf620000,0x3ef1bf80,0x3e953f35,0xbf753f35,
0x3dc93f55,0xbf7f3f0e,0x3f22bf7b,0x3f463e48,0x3f46bf6d,0x3f223ec4,0xbf7f3ec4,0x3dc9bf6d,0xbf753e48,0x3e95bf7b,0x3ef13f0e,0xbf623f55,
0x3f0ebf80,0x3f550000,0xbf550000,0x3f0ebf80,0xbf7b3ec4,0x3e48bf6d,0xbe483f6d,0xbf7b3ec4,0x3e483f35,0xbf7b3f35,0x3f7bbf35,0x3e483f35,
0x3f55bf6d,0x3f0e3ec4,0xbf0ebec4,0x3f55bf6d,0x3f460000,0xbf223f80,0x3f7fbf35,0x3dc93f35,0x3ef1bf7b,0x3f62be48,0xbe95bf0e,0x3f75bf55,
0xbf753ec4,0x3e95bf6d,0xbf623f6d,0xbef1bec4,0xbdc93f55,0xbf7f3f0e,0x3f223e48,0xbf463f7b,0xbf353f80,0xbf350000,0xbf353f80,0xbf350000,
0x3f350000,0xbf353f80,0x3f350000,0xbf353f80,0x3f35bf80,0x3f350000,0x3f35bf80,0x3f350000,0xbf350000,0x3f35bf80,0xbf350000,0x3f35bf80,
0xbf220000,0x3f46bf80,0x3dc9bf35,0x3f7fbf35,0xbf623f7b,0xbef1be48,0xbf753f0e,0x3e95bf55,0x3e953ec4,0xbf753f6d,0xbef13f6d,0xbf623ec4,
0x3f7fbf55,0x3dc93f0e,0x3f46be48,0xbf223f7b,0x3f55bf80,0x3f0e0000,0x3f0e0000,0xbf553f80,0xbe48bec4,0x3f7bbf6d,0x3f7bbf6d,0x3e483ec4,
0xbf7b3f35,0x3e48bf35,0x3e48bf35,0x3f7bbf35,0xbf0e3f6d,0xbf553ec4,0xbf553ec4,0x3f0ebf6d,0x3ef10000,0xbf623f80,0xbf753f35,0x3e95bf35,
0x3f7fbf55,0xbdc93f0e,0xbf463f7b,0xbf223e48,0x3f22bf6d,0x3f46bec4,0x3dc93ec4,0xbf7f3f6d,0xbe95be48,0x3f75bf7b,0x3f62bf0e,0xbef13f55,
0xbf6d3f80,0xbec40000,0x3f6dbf80,0x3ec40000,0xbec43f35,0xbf6d3f35,0x3ec4bf35,0x3f6dbf35,0x3ec40000,0xbf6d3f80,0xbec40000,0x3f6dbf80,
0x3f6dbf35,0xbec43f35,0xbf6d3f35,0x3ec4bf35,0xbe950000,0x3f75bf80,0xbef13f35,0xbf623f35,0xbf463f0e,0x3f22bf55,0x3dc93e48,0xbf7f3f7b,
0xbf7f3f6d,0x3dc9bec4,0x3f22bec4,0xbf463f6d,0xbf623f7b,0xbef13e48,0x3f75bf55,0xbe953f0e,0x3f7bbf80,0x3e480000,0xbe480000,0x3f7bbf80,
0x3f55bf6d,0x3f0ebec4,0xbf0e3ec4,0x3f55bf6d,0x3f0ebf35,0x3f55bf35,0xbf553f35,0x3f0ebf35,0x3e48bec4,0x3f7bbf6d,0xbf7b3f6d,0x3e48bec4,
0x3dc90000,0xbf7f3f80,0x3f46bf35,0xbf223f35,0x3e95be48,0xbf753f7b,0x3f62bf55,0xbef13f0e,0x3ef1bec4,0xbf623f6d,0x3f75bf6d,0xbe953ec4,
0x3f22bf0e,0xbf463f55,0x3f7fbf7b,0xbdc93e48,0x3f803f80,0xbf803f80,0x3f803f80,0xbf803f80,0x3f803f80,0xbf803f80,0x3f803f80,0xbf803f80,
0x3f803f80,0xbf803f80,0x3f803f80,0xbf803f80,0x3f803f80,0xbf803f80,0x3f803f80,0xbf803f80,0xbf7fbf80,0x3dc90000,0xbf22bf35,0x3f463f35,
0xbf75bf7b,0x3e953e48,0xbef1bf0e,0x3f623f55,0xbf62bf6d,0x3ef13ec4,0xbe95bec4,0x3f753f6d,0xbf46bf55,0x3f223f0e,0xbdc9be48,0x3f7f3f7b,
0x3f7b3f80,0xbe480000,0xbe480000,0xbf7bbf80,0x3f553f6d,0xbf0ebec4,0xbf0ebec4,0xbf55bf6d,0x3f0e3f35,0xbf55bf35,0xbf55bf35,0xbf0ebf35,
0x3e483ec4,0xbf7bbf6d,0xbf7bbf6d,0xbe48bec4,0xbf75bf80,0x3e950000,0x3f623f35,0x3ef13f35,0xbf22bf55,0x3f463f0e,0x3f7f3f7b,0xbdc93e48,
0xbdc9bec4,0x3f7f3f6d,0x3f463f6d,0xbf22bec4,0x3ef13e48,0x3f623f7b,0x3e953f0e,0xbf75bf55,0x3f6d3f80,0xbec40000,0xbf6dbf80,0x3ec40000,
0x3ec43f35,0xbf6dbf35,0xbec4bf35,0x3f6d3f35,0xbec40000,0xbf6dbf80,0x3ec40000,0x3f6d3f80,0xbf6dbf35,0xbec4bf35,0x3f6d3f35,0x3ec43f35,
0xbf62bf80,0x3ef10000,0x3e953f35,0xbf75bf35,0xbdc9bf0e,0x3f7f3f55,0xbf22be48,0xbf46bf7b,0x3f463ec4,0x3f223f6d,0xbf7fbf6d,0x3dc9bec4,
0x3f753f7b,0xbe953e48,0xbef1bf55,0x3f623f0e,0x3f553f80,0xbf0e0000,0x3f0e0000,0x3f553f80,0xbe483ec4,0xbf7bbf6d,0x3f7b3f6d,0xbe483ec4,
0xbf7bbf35,0xbe48bf35,0x3e483f35,0xbf7bbf35,0xbf0ebf6d,0x3f553ec4,0xbf55bec4,0xbf0ebf6d,0xbf46bf80,0x3f220000,0xbf7fbf35,0xbdc9bf35,
0x3ef1be48,0x3f623f7b,0xbe95bf55,0x3f753f0e,0x3f753f6d,0xbe953ec4,0x3f623ec4,0x3ef13f6d,0xbdc93f0e,0xbf7fbf55,0x3f223f7b,0xbf46be48,
0x3f353f80,0xbf350000,0x3f353f80,0xbf350000,0xbf350000,0xbf35bf80,0xbf350000,0xbf35bf80,0xbf35bf80,0x3f350000,0xbf35bf80,0x3f350000,
0x3f350000,0x3f353f80,0x3f350000,0x3f353f80,0xbf22bf80,0x3f460000,0x3dc9bf35,0x3f7f3f35,0x3f623e48,0x3ef13f7b,0x3f753f55,0xbe953f0e,
0x3e953f6d,0xbf75bec4,0xbef13ec4,0xbf62bf6d,0xbf7fbf0e,0xbdc9bf55,0xbf46bf7b,0x3f22be48,0x3f0e3f80,0xbf550000,0xbf550000,0xbf0ebf80,
0xbf7bbec4,0xbe48bf6d,0xbe48bf6d,0x3f7b3ec4,0x3e48bf35,0x3f7b3f35,0x3f7b3f35,0xbe483f35,0x3f553f6d,0xbf0e3ec4,0xbf0e3ec4,0xbf55bf6d,
0xbef1bf80,0x3f620000,0x3f753f35,0xbe953f35,0x3f7f3f0e,0xbdc93f55,0xbf463e48,0xbf22bf7b,0xbf223ec4,0xbf46bf6d,0xbdc9bf6d,0x3f7f3ec4,
0xbe95bf7b,0x3f753e48,0x3f623f55,0xbef13f0e,0x3ec43f80,0xbf6d0000,0xbec4bf80,0x3f6d0000,0xbf6dbf35,0x3ec4bf35,0x3f6d3f35,0xbec43f35,
0x3f6d0000,0x3ec43f80,0xbf6d0000,0xbec4bf80,0xbec43f35,0xbf6dbf35,0x3ec4bf35,0x3f6d3f35,0xbe95bf80,0x3f750000,0xbef13f35,0xbf62bf35,
0x3f463f55,0xbf223f0e,0xbdc9bf7b,0x3f7f3e48,0xbf7fbec4,0x3dc9bf6d,0x3f223f6d,0xbf463ec4,0x3f62be48,0x3ef13f7b,0xbf75bf0e,0x3e95bf55,
0x3e483f80,0xbf7b0000,0x3f7b0000,0x3e483f80,0xbf0ebf6d,0x3f55bec4,0xbf553ec4,0xbf0ebf6d,0x3f553f35,0xbf0e3f35,0x3f0ebf35,0x3f553f35,
0xbf7bbec4,0x3e48bf6d,0xbe483f6d,0xbf7bbec4,0xbdc9bf80,0x3f7f0000,0xbf46bf35,0x3f22bf35,0x3e953f7b,0xbf753e48,0x3f623f0e,0xbef13f55,
0xbef1bf6d,0x3f62bec4,0xbf75bec4,0x3e95bf6d,0x3f223f55,0xbf463f0e,0x3f7f3e48,0xbdc93f7b,0x3f80,0xbf800000,0x3f80,0xbf800000,
0xbf80,0x3f800000,0xbf80,0x3f800000,0x3f80,0xbf800000,0x3f80,0xbf800000,0xbf80,0x3f800000,0xbf80,0x3f800000,
0x3dc9bf80,0x3f7f0000,0x3f46bf35,0x3f223f35,0xbe953f7b,0xbf75be48,0xbf623f0e,0xbef1bf55,0x3ef1bf6d,0x3f623ec4,0x3f75bec4,0x3e953f6d,
0xbf223f55,0xbf46bf0e,0xbf7f3e48,0xbdc9bf7b,0xbe483f80,0xbf7b0000,0xbf7b0000,0x3e48bf80,0x3f0ebf6d,0x3f553ec4,0x3f553ec4,0xbf0e3f6d,
0xbf553f35,0xbf0ebf35,0xbf0ebf35,0x3f55bf35,0x3f7bbec4,0x3e483f6d,0x3e483f6d,0xbf7b3ec4,0x3e95bf80,0x3f750000,0x3ef13f35,0xbf623f35,
0xbf463f55,0xbf22bf0e,0x3dc9bf7b,0x3f7fbe48,0x3f7fbec4,0x3dc93f6d,0xbf223f6d,0xbf46bec4,0xbf62be48,0x3ef1bf7b,0x3f75bf0e,0x3e953f55,
0xbec43f80,0xbf6d0000,0x3ec4bf80,0x3f6d0000,0x3f6dbf35,0x3ec43f35,0xbf6d3f35,0xbec4bf35,0xbf6d0000,0x3ec4bf80,0x3f6d0000,0xbec43f80,
0x3ec43f35,0xbf6d3f35,0xbec4bf35,0x3f6dbf35,0x3ef1bf80,0x3f620000,0xbf753f35,0xbe95bf35,0xbf7f3f0e,0xbdc9bf55,0x3f463e48,0xbf223f7b,
0x3f223ec4,0xbf463f6d,0x3dc9bf6d,0x3f7fbec4,0x3e95bf7b,0x3f75be48,0xbf623f55,0xbef1bf0e,0xbf0e3f80,0xbf550000,0x3f550000,0xbf0e3f80,
0x3f7bbec4,0xbe483f6d,0x3e48bf6d,0x3f7bbec4,0xbe48bf35,0x3f7bbf35,0xbf7b3f35,0xbe48bf35,0xbf553f6d,0xbf0ebec4,0x3f0e3ec4,0xbf553f6d,
0x3f22bf80,0x3f460000,0xbdc9bf35,0x3f7fbf35,0xbf623e48,0x3ef1bf7b,0xbf753f55,0xbe95bf0e,0xbe953f6d,0xbf753ec4,0x3ef13ec4,0xbf623f6d,
0x3f7fbf0e,0xbdc93f55,0x3f46bf7b,0x3f223e48,0xbf353f80,0xbf350000,0xbf353f80,0xbf350000,0x3f350000,0xbf353f80,0x3f350000,0xbf353f80,
0x3f35bf80,0x3f350000,0x3f35bf80,0x3f350000,0xbf350000,0x3f35bf80,0xbf350000,0x3f35bf80,0x3f46bf80,0x3f220000,0x3f7fbf35,0xbdc93f35,
0xbef1be48,0x3f62bf7b,0x3e95bf55,0x3f75bf0e,0xbf753f6d,0xbe95bec4,0xbf623ec4,0x3ef1bf6d,0x3dc93f0e,0xbf7f3f55,0xbf223f7b,0xbf463e48,
0xbf553f80,0xbf0e0000,0xbf0e0000,0x3f55bf80,0x3e483ec4,0xbf7b3f6d,0xbf7b3f6d,0xbe48bec4,0x3f7bbf35,0xbe483f35,0xbe483f35,0xbf7b3f35,
0x3f0ebf6d,0x3f55bec4,0x3f55bec4,0xbf0e3f6d,0x3f62bf80,0x3ef10000,0xbe953f35,0xbf753f35,0x3dc9bf0e,0x3f7fbf55,0x3f22be48,0xbf463f7b,
0xbf463ec4,0x3f22bf6d,0x3f7fbf6d,0x3dc93ec4,0xbf753f7b,0xbe95be48,0x3ef1bf55,0x3f62bf0e,0xbf6d3f80,0xbec40000,0x3f6dbf80,0x3ec40000,
0xbec43f35,0xbf6d3f35,0x3ec4bf35,0x3f6dbf35,0x3ec40000,0xbf6d3f80,0xbec40000,0x3f6dbf80,0x3f6dbf35,0xbec43f35,0xbf6d3f35,0x3ec4bf35,
0x3f75bf80,0x3e950000,0xbf623f35,0x3ef1bf35,0x3f22bf55,0x3f46bf0e,0xbf7f3f7b,0xbdc9be48,0x3dc9bec4,0x3f7fbf6d,0xbf463f6d,0xbf223ec4,
0xbef13e48,0x3f62bf7b,0xbe953f0e,0xbf753f55,0xbf7b3f80,0xbe480000,0x3e480000,0xbf7b3f80,0xbf553f6d,0xbf0e3ec4,0x3f0ebec4,0xbf553f6d,
0xbf0e3f35,0xbf553f35,0x3f55bf35,0xbf0e3f35,0xbe483ec4,0xbf7b3f6d,0x3f7bbf6d,0xbe483ec4,0x3f7fbf80,0x3dc90000,0x3f22bf35,0x3f46bf35,
0x3f75bf7b,0x3e95be48,0x3ef1bf0e,0x3f62bf55,0x3f62bf6d,0x3ef1bec4,0x3e95bec4,0x3f75bf6d,0x3f46bf55,0x3f22bf0e,0x3dc9be48,0x3f7fbf7b,
0x3f803f80,0xbf803f80,0x3f803f80,0xbf803f80,0x3f803f80,0xbf803f80,0x3f803f80,0xbf803f80,0x3f803f80,0xbf803f80,0x3f803f80,0xbf803f80,
0x3f803f80,0xbf803f80,0x3f803f80,0xbf803f80,0x3dc90000,0x3f7f3f80,0x3f463f35,0x3f223f35,0x3e953e48,0x3f753f7b,0x3f623f55,0x3ef13f0e,
0x3ef13ec4,0x3f623f6d,0x3f753f6d,0x3e953ec4,0x3f223f0e,0x3f463f55,0x3f7f3f7b,0x3dc93e48,0xbf7bbf80,0x3e480000,0x3e480000,0x3f7b3f80,
0xbf55bf6d,0x3f0e3ec4,0x3f0e3ec4,0x3f553f6d,0xbf0ebf35,0x3f553f35,0x3f553f35,0x3f0e3f35,0xbe48bec4,0x3f7b3f6d,0x3f7b3f6d,0x3e483ec4,
0xbe950000,0xbf75bf80,0xbef1bf35,0x3f623f35,0xbf46bf0e,0xbf22bf55,0x3dc9be48,0x3f7f3f7b,0xbf7fbf6d,0xbdc9bec4,0x3f223ec4,0x3f463f6d,
0xbf62bf7b,0x3ef13e48,0x3f753f55,0x3e953f0e,0x3f6d3f80,0xbec40000,0xbf6dbf80,0x3ec40000,0x3ec43f35,0xbf6dbf35,0xbec4bf35,0x3f6d3f35,
0xbec40000,0xbf6dbf80,0x3ec40000,0x3f6d3f80,0xbf6dbf35,0xbec4bf35,0x3f6d3f35,0x3ec43f35,0x3ef10000,0x3f623f80,0xbf75bf35,0xbe95bf35,
0x3f7f3f55,0x3dc93f0e,0xbf46bf7b,0x3f223e48,0x3f223f6d,0xbf46bec4,0x3dc9bec4,0x3f7f3f6d,0xbe953e48,0xbf75bf7b,0x3f623f0e,0x3ef13f55,
0xbf55bf80,0x3f0e0000,0xbf0e0000,0xbf55bf80,0x3e48bec4,0x3f7b3f6d,0xbf7bbf6d,0x3e48bec4,0x3f7b3f35,0x3e483f35,0xbe48bf35,0x3f7b3f35,
0x3f0e3f6d,0xbf55bec4,0x3f553ec4,0x3f0e3f6d,0xbf220000,0xbf46bf80,0x3dc93f35,0xbf7fbf35,0xbf62bf7b,0x3ef1be48,0xbf75bf0e,0xbe95bf55,
0x3e95bec4,0x3f753f6d,0xbef1bf6d,0x3f623ec4,0x3f7f3f55,0xbdc93f0e,0x3f463e48,0x3f223f7b,0x3f353f80,0xbf350000,0x3f353f80,0xbf350000,
0xbf350000,0xbf35bf80,0xbf350000,0xbf35bf80,0xbf35bf80,0x3f350000,0xbf35bf80,0x3f350000,0x3f350000,0x3f353f80,0x3f350000,0x3f353f80,
0x3f460000,0x3f223f80,0x3f7f3f35,0xbdc93f35,0x3ef13f7b,0xbf62be48,0xbe953f0e,0xbf75bf55,0xbf75bec4,0xbe95bf6d,0xbf62bf6d,0x3ef1bec4,
0xbdc9bf55,0x3f7f3f0e,0x3f22be48,0x3f463f7b,0xbf0ebf80,0x3f550000,0x3f550000,0x3f0e3f80,0x3f7b3ec4,0x3e483f6d,0x3e483f6d,0xbf7bbec4,
0xbe483f35,0xbf7bbf35,0xbf7bbf35,0x3e48bf35,0xbf55bf6d,0x3f0ebec4,0x3f0ebec4,0x3f553f6d,0xbf620000,0xbef1bf80,0x3e95bf35,0x3f753f35,
0x3dc9bf55,0x3f7f3f0e,0x3f223f7b,0xbf463e48,0x3f463f6d,0xbf223ec4,0xbf7fbec4,0xbdc9bf6d,0xbf75be48,0xbe95bf7b,0x3ef1bf0e,0x3f623f55,
0x3ec43f80,0xbf6d0000,0xbec4bf80,0x3f6d0000,0xbf6dbf35,0x3ec4bf35,0x3f6d3f35,0xbec43f35,0x3f6d0000,0x3ec43f80,0xbf6d0000,0xbec4bf80,
0xbec43f35,0xbf6dbf35,0x3ec4bf35,0x3f6d3f35,0x3f750000,0x3e953f80,0xbf62bf35,0x3ef1bf35,0xbf223f0e,0xbf46bf55,0x3f7f3e48,0x3dc93f7b,
0x3dc9bf6d,0x3f7f3ec4,0xbf463ec4,0xbf22bf6d,0x3ef13f7b,0xbf623e48,0x3e95bf55,0x3f753f0e,0xbe48bf80,0x3f7b0000,0xbf7b0000,0xbe48bf80,
0x3f0e3f6d,0xbf553ec4,0x3f55bec4,0x3f0e3f6d,0xbf55bf35,0x3f0ebf35,0xbf0e3f35,0xbf55bf35,0x3f7b3ec4,0xbe483f6d,0x3e48bf6d,0x3f7b3ec4,
0xbf7f0000,0xbdc9bf80,0xbf223f35,0xbf46bf35,0x3f75be48,0x3e953f7b,0x3ef1bf55,0x3f623f0e,0xbf623ec4,0xbef1bf6d,0xbe953f6d,0xbf75bec4,
0x3f46bf0e,0x3f223f55,0x3dc9bf7b,0x3f7f3e48,0x3f80,0xbf800000,0x3f80,0xbf800000,0xbf80,0x3f800000,0xbf80,0x3f800000,
0x3f80,0xbf800000,0x3f80,0xbf800000,0xbf80,0x3f800000,0xbf80,0x3f800000,0x3f7f0000,0xbdc93f80,0x3f223f35,0xbf463f35,
0xbf75be48,0x3e95bf7b,0xbef1bf55,0x3f62bf0e,0x3f623ec4,0xbef13f6d,0x3e953f6d,0xbf753ec4,0xbf46bf0e,0x3f22bf55,0xbdc9bf7b,0x3f7fbe48,
0x3e48bf80,0x3f7b0000,0x3f7b0000,0xbe483f80,0xbf0e3f6d,0xbf55bec4,0xbf55bec4,0x3f0ebf6d,0x3f55bf35,0x3f0e3f35,0x3f0e3f35,0xbf553f35,
0xbf7b3ec4,0xbe48bf6d,0xbe48bf6d,0x3f7bbec4,0xbf750000,0x3e95bf80,0x3f62bf35,0x3ef13f35,0x3f223f0e,0xbf463f55,0xbf7f3e48,0x3dc9bf7b,
0xbdc9bf6d,0x3f7fbec4,0x3f463ec4,0xbf223f6d,0xbef13f7b,0xbf62be48,0xbe95bf55,0x3f75bf0e,0xbec43f80,0xbf6d0000,0x3ec4bf80,0x3f6d0000,
0x3f6dbf35,0x3ec43f35,0xbf6d3f35,0xbec4bf35,0xbf6d0000,0x3ec4bf80,0x3f6d0000,0xbec43f80,0x3ec43f35,0xbf6d3f35,0xbec4bf35,0x3f6dbf35,
0x3f620000,0xbef13f80,0xbe95bf35,0x3f75bf35,0xbdc9bf55,0x3f7fbf0e,0xbf223f7b,0xbf46be48,0xbf463f6d,0xbf22bec4,0x3f7fbec4,0xbdc93f6d,
0x3f75be48,0xbe953f7b,0xbef1bf0e,0x3f62bf55,0x3f0ebf80,0x3f550000,0xbf550000,0x3f0ebf80,0xbf7b3ec4,0x3e48bf6d,0xbe483f6d,0xbf7b3ec4,
0x3e483f35,0xbf7b3f35,0x3f7bbf35,0x3e483f35,0x3f55bf6d,0x3f0e3ec4,0xbf0ebec4,0x3f55bf6d,0xbf460000,0x3f22bf80,0xbf7f3f35,0xbdc9bf35,
0xbef13f7b,0xbf623e48,0x3e953f0e,0xbf753f55,0x3f75bec4,0xbe953f6d,0x3f62bf6d,0x3ef13ec4,0x3dc9bf55,0x3f7fbf0e,0xbf22be48,0x3f46bf7b,
0xbf353f80,0xbf350000,0xbf353f80,0xbf350000,0x3f350000,0xbf353f80,0x3f350000,0xbf353f80,0x3f35bf80,0x3f350000,0x3f35bf80,0x3f350000,
0xbf350000,0x3f35bf80,0xbf350000,0x3f35bf80,0x3f220000,0xbf463f80,0xbdc93f35,0xbf7f3f35,0x3f62bf7b,0x3ef13e48,0x3f75bf0e,0xbe953f55,
0xbe95bec4,0x3f75bf6d,0x3ef1bf6d,0x3f62bec4,0xbf7f3f55,0xbdc9bf0e,0xbf463e48,0x3f22bf7b,0x3f55bf80,0x3f0e0000,0x3f0e0000,0xbf553f80,
0xbe48bec4,0x3f7bbf6d,0x3f7bbf6d,0x3e483ec4,0xbf7b3f35,0x3e48bf35,0x3e48bf35,0x3f7bbf35,0xbf0e3f6d,0xbf553ec4,0xbf553ec4,0x3f0ebf6d,
0xbef10000,0x3f62bf80,0x3f75bf35,0xbe953f35,0xbf7f3f55,0x3dc9bf0e,0x3f46bf7b,0x3f22be48,0xbf223f6d,0xbf463ec4,0xbdc9bec4,0x3f7fbf6d,
0x3e953e48,0xbf753f7b,0xbf623f0e,0x3ef1bf55,0xbf6d3f80,0xbec40000,0x3f6dbf80,0x3ec40000,0xbec43f35,0xbf6d3f35,0x3ec4bf35,0x3f6dbf35,
0x3ec40000,0xbf6d3f80,0xbec40000,0x3f6dbf80,0x3f6dbf35,0xbec43f35,0xbf6d3f35,0x3ec4bf35,0x3e950000,0xbf753f80,0x3ef1bf35,0x3f62bf35,
0x3f46bf0e,0xbf223f55,0xbdc9be48,0x3f7fbf7b,0x3f7fbf6d,0xbdc93ec4,0xbf223ec4,0x3f46bf6d,0x3f62bf7b,0x3ef1be48,0xbf753f55,0x3e95bf0e,
0x3f7bbf80,0x3e480000,0xbe480000,0x3f7bbf80,0x3f55bf6d,0x3f0ebec4,0xbf0e3ec4,0x3f55bf6d,0x3f0ebf35,0x3f55bf35,0xbf553f35,0x3f0ebf35,
0x3e48bec4,0x3f7bbf6d,0xbf7b3f6d,0x3e48bec4,0xbdc90000,0x3f7fbf80,0xbf463f35,0x3f22bf35,0xbe953e48,0x3f75bf7b,0xbf623f55,0x3ef1bf0e,
0xbef13ec4,0x3f62bf6d,0xbf753f6d,0x3e95bec4,0xbf223f0e,0x3f46bf55,0xbf7f3f7b,0x3dc9be48,0x40003f80,0x3fb53f80,0x3f80,0xbfb53f80,
0x40004000,0xbfb50000,0x0,0xbfb5c000,0x40004000,0xbfb5c000,0x0,0x3fb50000,0x40004000,0x3fb50000,0x0,0x3fb54000,
0x3fff3f80,0x3fa23f80,0xbe49bf80,0xbfc6bf80,0x3ff53ffb,0xbfe2bec8,0xbf15bec8,0xbf71bffb,0x3fe23fed,0xbf15bfed,0xbf71bf44,0x3ff53f44,
0x3fc63fd5,0x3fff3f8e,0xbfa2bf8e,0x3e493fd5,0x3ffb3f80,0x3f8e3f80,0xbec83f80,0xbfd53f80,0x3fd53fed,0xbffbbf44,0xbf8ebf44,0xbec8bfed,
0x3f8e3fb5,0x3ec8bfb5,0xbfd5bfb5,0x3ffb3fb5,0x3ec83f44,0x3fd53fed,0xbffbbfed,0xbf8e3f44,0x3ff53f80,0x3f713f80,0xbf15bf80,0xbfe2bf80,
0x3fa23fd5,0xbfffbf8e,0xbfc6bf8e,0x3e49bfd5,0x3e493f44,0x3fa2bf44,0xbfffbfed,0x3fc63fed,0xbf71bec8,0x3f153ffb,0xbfe2bffb,0xbff5bec8,
0x3fed3f80,0x3f443f80,0xbf443f80,0xbfed3f80,0x3f443fb5,0xbfedbfb5,0xbfedbfb5,0x3f44bfb5,0xbf440000,0x3fed0000,0xbfedc000,0x3f444000,
0xbfedbfb5,0xbf443fb5,0xbf44bfb5,0xbfedbfb5,0x3fe23f80,0x3f153f80,0xbf71bf80,0xbff5bf80,0x3e493f8e,0xbfc6bfd5,0xbfffbfd5,0x3fa2bf8e,
0xbfc6bf44,0x3fff3f44,0xbfa2bfed,0xbe493fed,0xbff5bffb,0xbfe23ec8,0x3f15bec8,0xbf71bffb,0x3fd53f80,0x3ec83f80,0xbf8e3f80,0xbffb3f80,
0xbec83f44,0xbf8ebfed,0xbffbbfed,0x3fd5bf44,0xbffbbfb5,0x3fd53fb5,0xbec8bfb5,0xbf8e3fb5,0xbf8ebfed,0xbffbbf44,0x3fd53f44,0x3ec8bfed,
0x3fc63f80,0x3e493f80,0xbfa2bf80,0xbfffbf80,0xbf713ec8,0xbf15bffb,0xbfe2bffb,0x3ff5bec8,0xbff5bfed,0x3f713fed,0x3f15bf44,0xbfe23f44,
0x3e49bf8e,0xbfa2bfd5,0x3fff3fd5,0x3fc6bf8e,0x3f80,0xbfb53f80,0xc0003f80,0xbfb53f80,0xc000,0x3fb50000,0x40000000,0xbfb54000,
0x4000,0x3fb5c000,0xc0000000,0x3fb50000,0xc000,0xbfb50000,0x40000000,0x3fb5c000,0xbe493f80,0xbfc63f80,0xbfffbf80,0xbfa2bf80,
0x3f15bffb,0x3f713ec8,0x3ff53ec8,0xbfe23ffb,0xbf713fed,0x3ff5bfed,0xbfe2bf44,0x3f153f44,0x3fa2bfd5,0xbe49bf8e,0x3fc63f8e,0x3fffbfd5,
0xbec83f80,0xbfd53f80,0xbffb3f80,0xbf8e3f80,0x3f8ebfed,0x3ec83f44,0x3fd53f44,0xbffb3fed,0xbfd53fb5,0x3ffbbfb5,0xbf8ebfb5,0xbec83fb5,
0x3ffbbf44,0x3f8ebfed,0x3ec83fed,0x3fd5bf44,0xbf153f80,0xbfe23f80,0xbff5bf80,0xbf71bf80,0x3fc6bfd5,0xbe493f8e,0x3fa23f8e,0xbfff3fd5,
0xbfff3f44,0x3fc6bf44,0xbe49bfed,0xbfa23fed,0x3fe23ec8,0x3ff5bffb,0xbf713ffb,0x3f153ec8,0xbf443f80,0xbfed3f80,0xbfed3f80,0xbf443f80,
0x3fedbfb5,0xbf443fb5,0x3f443fb5,0xbfed3fb5,0xbfed0000,0x3f440000,0x3f44c000,0xbfed4000,0x3f443fb5,0x3fedbfb5,0xbfed3fb5,0xbf443fb5,
0xbf713f80,0xbff53f80,0xbfe2bf80,0xbf15bf80,0x3fffbf8e,0xbfa23fd5,0x3e493fd5,0xbfc63f8e,0xbfa2bf44,0xbe493f44,0x3fc6bfed,0xbfff3fed,
0xbf153ffb,0x3f71bec8,0xbff53ec8,0xbfe23ffb,0xbf8e3f80,0xbffb3f80,0xbfd53f80,0xbec83f80,0x3ffbbf44,0xbfd53fed,0xbec83fed,0xbf8e3f44,
0xbec8bfb5,0xbf8e3fb5,0x3ffbbfb5,0xbfd53fb5,0xbfd53fed,0xbec83f44,0xbf8ebf44,0xbffb3fed,0xbfa23f80,0xbfff3f80,0xbfc6bf80,0xbe49bf80,
0x3fe2bec8,0xbff53ffb,0xbf713ffb,0xbf153ec8,0x3f15bfed,0xbfe23fed,0x3ff5bf44,0xbf713f44,0xbfff3f8e,0xbfc63fd5,0x3e49bfd5,0xbfa23f8e,
0xc0003f80,0xbfb53f80,0x3f80,0x3fb53f80,0xc0004000,0x3fb50000,0x0,0x3fb5c000,0xc0004000,0x3fb5c000,0x0,0xbfb50000,
0xc0004000,0xbfb50000,0x0,0xbfb54000,0xbfff3f80,0xbfa23f80,0x3e49bf80,0x3fc6bf80,0xbff53ffb,0x3fe2bec8,0x3f15bec8,0x3f71bffb,
0xbfe23fed,0x3f15bfed,0x3f71bf44,0xbff53f44,0xbfc63fd5,0xbfff3f8e,0x3fa2bf8e,0xbe493fd5,0xbffb3f80,0xbf8e3f80,0x3ec83f80,0x3fd53f80,
0xbfd53fed,0x3ffbbf44,0x3f8ebf44,0x3ec8bfed,0xbf8e3fb5,0xbec8bfb5,0x3fd5bfb5,0xbffb3fb5,0xbec83f44,0xbfd53fed,0x3ffbbfed,0x3f8e3f44,
0xbff53f80,0xbf713f80,0x3f15bf80,0x3fe2bf80,0xbfa23fd5,0x3fffbf8e,0x3fc6bf8e,0xbe49bfd5,0xbe493f44,0xbfa2bf44,0x3fffbfed,0xbfc63fed,
0x3f71bec8,0xbf153ffb,0x3fe2bffb,0x3ff5bec8,0xbfed3f80,0xbf443f80,0x3f443f80,0x3fed3f80,0xbf443fb5,0x3fedbfb5,0x3fedbfb5,0xbf44bfb5,
0x3f440000,0xbfed0000,0x3fedc000,0xbf444000,0x3fedbfb5,0x3f443fb5,0x3f44bfb5,0x3fedbfb5,0xbfe23f80,0xbf153f80,0x3f71bf80,0x3ff5bf80,
0xbe493f8e,0x3fc6bfd5,0x3fffbfd5,0xbfa2bf8e,0x3fc6bf44,0xbfff3f44,0x3fa2bfed,0x3e493fed,0x3ff5bffb,0x3fe23ec8,0xbf15bec8,0x3f71bffb,
0xbfd53f80,0xbec83f80,0x3f8e3f80,0x3ffb3f80,0x3ec83f44,0x3f8ebfed,0x3ffbbfed,0xbfd5bf44,0x3ffbbfb5,0xbfd53fb5,0x3ec8bfb5,0x3f8e3fb5,
0x3f8ebfed,0x3ffbbf44,0xbfd53f44,0xbec8bfed,0xbfc63f80,0xbe493f80,0x3fa2bf80,0x3fffbf80,0x3f713ec8,0x3f15bffb,0x3fe2bffb,0xbff5bec8,
0x3ff5bfed,0xbf713fed,0xbf15bf44,0x3fe23f44,0xbe49bf8e,0x3fa2bfd5,0xbfff3fd5,0xbfc6bf8e,0x3f80,0x3fb53f80,0x40003f80,0x3fb53f80,
0xc000,0xbfb50000,0xc0000000,0x3fb54000,0x4000,0xbfb5c000,0x40000000,0xbfb50000,0xc000,0x3fb50000,0xc0000000,0xbfb5c000,
0x3e493f80,0x3fc63f80,0x3fffbf80,0x3fa2bf80,0xbf15bffb,0xbf713ec8,0xbff53ec8,0x3fe23ffb,0x3f713fed,0xbff5bfed,0x3fe2bf44,0xbf153f44,
0xbfa2bfd5,0x3e49bf8e,0xbfc63f8e,0xbfffbfd5,0x3ec83f80,0x3fd53f80,0x3ffb3f80,0x3f8e3f80,0xbf8ebfed,0xbec83f44,0xbfd53f44,0x3ffb3fed,
0x3fd53fb5,0xbffbbfb5,0x3f8ebfb5,0x3ec83fb5,0xbffbbf44,0xbf8ebfed,0xbec83fed,0xbfd5bf44,0x3f153f80,0x3fe23f80,0x3ff5bf80,0x3f71bf80,
0xbfc6bfd5,0x3e493f8e,0xbfa23f8e,0x3fff3fd5,0x3fff3f44,0xbfc6bf44,0x3e49bfed,0x3fa23fed,0xbfe23ec8,0xbff5bffb,0x3f713ffb,0xbf153ec8,
0x3f443f80,0x3fed3f80,0x3fed3f80,0x3f443f80,0xbfedbfb5,0x3f443fb5,0xbf443fb5,0x3fed3fb5,0x3fed0000,0xbf440000,0xbf44c000,0x3fed4000,
0xbf443fb5,0xbfedbfb5,0x3fed3fb5,0x3f443fb5,0x3f713f80,0x3ff53f80,0x3fe2bf80,0x3f15bf80,0xbfffbf8e,0x3fa23fd5,0xbe493fd5,0x3fc63f8e,
0x3fa2bf44,0x3e493f44,0xbfc6bfed,0x3fff3fed,0x3f153ffb,0xbf71bec8,0x3ff53ec8,0x3fe23ffb,0x3f8e3f80,0x3ffb3f80,0x3fd53f80,0x3ec83f80,
0xbffbbf44,0x3fd53fed,0x3ec83fed,0x3f8e3f44,0x3ec8bfb5,0x3f8e3fb5,0xbffbbfb5,0x3fd53fb5,0x3fd53fed,0x3ec83f44,0x3f8ebf44,0x3ffb3fed,
0x3fa23f80,0x3fff3f80,0x3fc6bf80,0x3e49bf80,0xbfe2bec8,0x3ff53ffb,0x3f713ffb,0x3f153ec8,0xbf15bfed,0x3fe23fed,0xbff5bf44,0x3f713f44,
0x3fff3f8e,0x3fc63fd5,0xbe49bfd5,0x3fa23f8e,0x40004000,0x3fb54000,0x0,0xbfb50000,0x40004000,0xbfb50000,0x0,0xbfb5c000,
0x40004000,0xbfb5c000,0x0,0x3fb50000,0x40004000,0x3fb50000,0x0,0x3fb54000,0x3fa23fb5,0xbe493fb5,0xbfc6bfb5,0xbfffbfb5,
0x3f713f8e,0xbff5bfd5,0xbfe2bfd5,0x3f15bf8e,0x3f153f44,0x3f71bf44,0xbff5bfed,0x3fe23fed,0x3e493ec8,0x3fc63ffb,0xbfffbffb,0xbfa23ec8,
0xbec80000,0xbfd50000,0xbffbc000,0xbf8ec000,0xbf8ebf44,0xbec8bfed,0xbfd5bfed,0x3ffb3f44,0xbfd5bfb5,0x3ffb3fb5,0xbf8ebfb5,0xbec83fb5,
0xbffbbfed,0xbf8e3f44,0xbec8bf44,0xbfd5bfed,0xbfe2bfb5,0xbff5bfb5,0xbf71bfb5,0x3f15bfb5,0xbfffbffb,0x3fc6bec8,0x3e49bec8,0x3fa23ffb,
0xbfc6bfed,0x3e493fed,0x3fa23f44,0xbfffbf44,0xbf15bf8e,0xbfe2bfd5,0x3ff53fd5,0x3f71bf8e,0xbfedc000,0xbf44c000,0x3f440000,0x3fed0000,
0xbf44bfb5,0x3fed3fb5,0x3fed3fb5,0xbf443fb5,0x3f440000,0xbfed0000,0x3fed4000,0xbf44c000,0x3fed3fb5,0x3f44bfb5,0x3f443fb5,0x3fed3fb5,
0xbf15bfb5,0x3f71bfb5,0x3ff53fb5,0x3fe23fb5,0x3fa23ec8,0x3e493ffb,0x3fc63ffb,0xbfffbec8,0x3fff3fed,0xbfa2bfed,0xbe493f44,0x3fc6bf44,
0x3f713fd5,0x3ff53f8e,0xbfe2bf8e,0xbf153fd5,0x3f8e0000,0x3ffb0000,0x3fd54000,0x3ec84000,0x3ffb3fed,0xbfd53f44,0xbec83f44,0xbf8ebfed,
0x3ec83fb5,0x3f8ebfb5,0xbffbbfb5,0x3fd53fb5,0xbfd5bf44,0xbec83fed,0xbf8ebfed,0xbffbbf44,0x3fff3fb5,0x3fc63fb5,0x3e493fb5,0xbfa23fb5,
0x3f153fd5,0xbfe2bf8e,0xbff5bf8e,0x3f71bfd5,0xbfe2bf44,0x3ff53f44,0xbf71bfed,0xbf153fed,0xbfa2bffb,0xbfffbec8,0x3fc63ec8,0x3e49bffb,
0x4000,0xbfb54000,0xc0000000,0xbfb50000,0xc000,0x3fb50000,0x40000000,0xbfb54000,0x4000,0x3fb5c000,0xc0000000,0x3fb50000,
0xc000,0xbfb50000,0x40000000,0x3fb5c000,0xbfc63fb5,0xbfff3fb5,0xbfa2bfb5,0x3e49bfb5,0x3fe2bf8e,0xbf153fd5,0x3f713fd5,0xbff53f8e,
0xbff53f44,0x3fe2bf44,0xbf15bfed,0xbf713fed,0x3fffbec8,0x3fa2bffb,0x3e493ffb,0x3fc6bec8,0xbffb0000,0xbf8e0000,0x3ec8c000,0x3fd5c000,
0x3fd53f44,0xbffb3fed,0xbf8e3fed,0xbec8bf44,0xbf8ebfb5,0xbec83fb5,0x3fd5bfb5,0xbffb3fb5,0x3ec83fed,0x3fd5bf44,0xbffb3f44,0xbf8e3fed,
0xbf71bfb5,0x3f15bfb5,0x3fe2bfb5,0x3ff5bfb5,0xbe493ffb,0xbfa23ec8,0xbfff3ec8,0x3fc6bffb,0x3fa2bfed,0xbfff3fed,0x3fc63f44,0xbe49bf44,
0xbff53f8e,0xbf713fd5,0xbf15bfd5,0xbfe23f8e,0x3f44c000,0x3fedc000,0x3fed0000,0x3f440000,0xbfed3fb5,0x3f44bfb5,0xbf44bfb5,0x3fedbfb5,
0x3fed0000,0xbf440000,0xbf444000,0x3fedc000,0xbf44bfb5,0xbfed3fb5,0x3fedbfb5,0x3f44bfb5,0x3ff5bfb5,0x3fe2bfb5,0x3f153fb5,0xbf713fb5,
0xbfc6bec8,0x3fffbffb,0x3fa2bffb,0x3e493ec8,0xbe493fed,0x3fc6bfed,0xbfff3f44,0x3fa2bf44,0x3fe2bfd5,0x3f15bf8e,0x3f713f8e,0x3ff5bfd5,
0x3fd50000,0x3ec80000,0xbf8e4000,0xbffb4000,0x3ec8bfed,0x3f8ebf44,0x3ffbbf44,0xbfd53fed,0xbffb3fb5,0x3fd5bfb5,0xbec8bfb5,0xbf8e3fb5,
0x3f8e3f44,0x3ffbbfed,0xbfd53fed,0xbec83f44,0x3e493fb5,0xbfa23fb5,0xbfff3fb5,0xbfc63fb5,0x3ff5bfd5,0xbf713f8e,0x3f153f8e,0xbfe23fd5,
0xbf71bf44,0xbf153f44,0x3fe2bfed,0xbff53fed,0xbfc63ffb,0xbe493ec8,0xbfa2bec8,0xbfff3ffb,0xc0004000,0xbfb54000,0x0,0x3fb50000,
0xc0004000,0x3fb50000,0x0,0x3fb5c000,0xc0004000,0x3fb5c000,0x0,0xbfb50000,0xc0004000,0xbfb50000,0x0,0xbfb54000,
0xbfa23fb5,0x3e493fb5,0x3fc6bfb5,0x3fffbfb5,0xbf713f8e,0x3ff5bfd5,0x3fe2bfd5,0xbf15bf8e,0xbf153f44,0xbf71bf44,0x3ff5bfed,0xbfe23fed,
0xbe493ec8,0xbfc63ffb,0x3fffbffb,0x3fa23ec8,0x3ec80000,0x3fd50000,0x3ffbc000,0x3f8ec000,0x3f8ebf44,0x3ec8bfed,0x3fd5bfed,0xbffb3f44,
0x3fd5bfb5,0xbffb3fb5,0x3f8ebfb5,0x3ec83fb5,0x3ffbbfed,0x3f8e3f44,0x3ec8bf44,0x3fd5bfed,0x3fe2bfb5,0x3ff5bfb5,0x3f71bfb5,0xbf15bfb5,
0x3fffbffb,0xbfc6bec8,0xbe49bec8,0xbfa23ffb,0x3fc6bfed,0xbe493fed,0xbfa23f44,0x3fffbf44,0x3f15bf8e,0x3fe2bfd5,0xbff53fd5,0xbf71bf8e,
0x3fedc000,0x3f44c000,0xbf440000,0xbfed0000,0x3f44bfb5,0xbfed3fb5,0xbfed3fb5,0x3f443fb5,0xbf440000,0x3fed0000,0xbfed4000,0x3f44c000,
0xbfed3fb5,0xbf44bfb5,0xbf443fb5,0xbfed3fb5,0x3f15bfb5,0xbf71bfb5,0xbff53fb5,0xbfe23fb5,0xbfa23ec8,0xbe493ffb,0xbfc63ffb,0x3fffbec8,
0xbfff3fed,0x3fa2bfed,0x3e493f44,0xbfc6bf44,0xbf713fd5,0xbff53f8e,0x3fe2bf8e,0x3f153fd5,0xbf8e0000,0xbffb0000,0xbfd54000,0xbec84000,
0xbffb3fed,0x3fd53f44,0x3ec83f44,0x3f8ebfed,0xbec83fb5,0xbf8ebfb5,0x3ffbbfb5,0xbfd53fb5,0x3fd5bf44,0x3ec83fed,0x3f8ebfed,0x3ffbbf44,
0xbfff3fb5,0xbfc63fb5,0xbe493fb5,0x3fa23fb5,0xbf153fd5,0x3fe2bf8e,0x3ff5bf8e,0xbf71bfd5,0x3fe2bf44,0xbff53f44,0x3f71bfed,0x3f153fed,
0x3fa2bffb,0x3fffbec8,0xbfc63ec8,0xbe49bffb,0x4000,0x3fb54000,0x40000000,0x3fb50000,0xc000,0xbfb50000,0xc0000000,0x3fb54000,
0x4000,0xbfb5c000,0x40000000,0xbfb50000,0xc000,0x3fb50000,0xc0000000,0xbfb5c000,0x3fc63fb5,0x3fff3fb5,0x3fa2bfb5,0xbe49bfb5,
0xbfe2bf8e,0x3f153fd5,0xbf713fd5,0x3ff53f8e,0x3ff53f44,0xbfe2bf44,0x3f15bfed,0x3f713fed,0xbfffbec8,0xbfa2bffb,0xbe493ffb,0xbfc6bec8,
0x3ffb0000,0x3f8e0000,0xbec8c000,0xbfd5c000,0xbfd53f44,0x3ffb3fed,0x3f8e3fed,0x3ec8bf44,0x3f8ebfb5,0x3ec83fb5,0xbfd5bfb5,0x3ffb3fb5,
0xbec83fed,0xbfd5bf44,0x3ffb3f44,0x3f8e3fed,0x3f71bfb5,0xbf15bfb5,0xbfe2bfb5,0xbff5bfb5,0x3e493ffb,0x3fa23ec8,0x3fff3ec8,0xbfc6bffb,
0xbfa2bfed,0x3fff3fed,0xbfc63f44,0x3e49bf44,0x3ff53f8e,0x3f713fd5,0x3f15bfd5,0x3fe23f8e,0xbf44c000,0xbfedc000,0xbfed0000,0xbf440000,
0x3fed3fb5,0xbf44bfb5,0x3f44bfb5,0xbfedbfb5,0xbfed0000,0x3f440000,0x3f444000,0xbfedc000,0x3f44bfb5,0x3fed3fb5,0xbfedbfb5,0xbf44bfb5,
0xbff5bfb5,0xbfe2bfb5,0xbf153fb5,0x3f713fb5,0x3fc6bec8,0xbfffbffb,0xbfa2bffb,0xbe493ec8,0x3e493fed,0xbfc6bfed,0x3fff3f44,0xbfa2bf44,
0xbfe2bfd5,0xbf15bf8e,0xbf713f8e,0xbff5bfd5,0xbfd50000,0xbec80000,0x3f8e4000,0x3ffb4000,0xbec8bfed,0xbf8ebf44,0xbffbbf44,0x3fd53fed,
0x3ffb3fb5,0xbfd5bfb5,0x3ec8bfb5,0x3f8e3fb5,0xbf8e3f44,0xbffbbfed,0x3fd53fed,0x3ec83f44,0xbe493fb5,0x3fa23fb5,0x3fff3fb5,0x3fc63fb5,
0xbff5bfd5,0x3f713f8e,0xbf153f8e,0x3fe23fd5,0x3f71bf44,0x3f153f44,0xbfe2bfed,0x3ff53fed,0x3fc63ffb,0x3e493ec8,0x3fa2bec8,0x3fff3ffb,
0x40004000,0x3fb54000,0x0,0xbfb50000,0x40004000,0xbfb50000,0x0,0xbfb5c000,0x40004000,0xbfb5c000,0x0,0x3fb50000,
0x40004000,0x3fb50000,0x0,0x3fb54000,0xbe490000,0xbfc60000,0xbfffc000,0xbfa2c000,0xbf15bec8,0xbf71bffb,0xbff5bffb,0x3fe23ec8,
0xbf71bf44,0x3ff53f44,0xbfe2bfed,0x3f153fed,0xbfa2bf8e,0x3e493fd5,0xbfc6bfd5,0xbfffbf8e,0xbffbc000,0xbf8ec000,0x3ec80000,0x3fd50000,
0xbfd5bfed,0x3ffb3f44,0x3f8e3f44,0x3ec83fed,0xbf8ebfb5,0xbec83fb5,0x3fd53fb5,0xbffbbfb5,0xbec8bf44,0xbfd5bfed,0x3ffb3fed,0x3f8ebf44,
0x3f150000,0x3fe20000,0x3ff54000,0x3f714000,0x3fc63f8e,0xbe493fd5,0x3fa23fd5,0xbfffbf8e,0x3fff3fed,0xbfc6bfed,0x3e493f44,0x3fa2bf44,
0x3fe23ffb,0x3ff53ec8,0xbf71bec8,0x3f153ffb,0x3fed4000,0x3f444000,0xbf440000,0xbfed0000,0x3f443fb5,0xbfedbfb5,0xbfedbfb5,0x3f44bfb5,
0xbf440000,0x3fed0000,0xbfedc000,0x3f444000,0xbfedbfb5,0xbf443fb5,0xbf44bfb5,0xbfedbfb5,0xbf710000,0xbff50000,0xbfe2c000,0xbf15c000,
0xbfffbfd5,0x3fa2bf8e,0xbe49bf8e,0x3fc63fd5,0xbfa2bfed,0xbe493fed,0x3fc63f44,0xbfffbf44,0x3f15bec8,0xbf71bffb,0x3ff53ffb,0x3fe2bec8,
0xbfd5c000,0xbec8c000,0x3f8e0000,0x3ffb0000,0x3ec8bf44,0x3f8e3fed,0x3ffb3fed,0xbfd53f44,0x3ffb3fb5,0xbfd5bfb5,0x3ec83fb5,0x3f8ebfb5,
0x3f8e3fed,0x3ffb3f44,0xbfd5bf44,0xbec83fed,0x3fa20000,0x3fff0000,0x3fc64000,0x3e494000,0x3fe23ffb,0xbff53ec8,0xbf713ec8,0xbf15bffb,
0xbf153f44,0x3fe2bf44,0xbff5bfed,0x3f713fed,0xbfffbfd5,0xbfc63f8e,0x3e49bf8e,0xbfa2bfd5,0x4000,0xbfb54000,0xc0000000,0xbfb50000,
0xc000,0x3fb50000,0x40000000,0xbfb54000,0x4000,0x3fb5c000,0xc0000000,0x3fb50000,0xc000,0xbfb50000,0x40000000,0x3fb5c000,
0xbfff0000,0xbfa20000,0x3e49c000,0x3fc6c000,0x3ff53ec8,0xbfe23ffb,0xbf153ffb,0xbf71bec8,0xbfe2bf44,0x3f153f44,0x3f71bfed,0xbff53fed,
0x3fc63f8e,0x3fffbfd5,0xbfa23fd5,0x3e493f8e,0x3ec8c000,0x3fd5c000,0x3ffb0000,0x3f8e0000,0xbf8e3fed,0xbec8bf44,0xbfd5bf44,0x3ffbbfed,
0x3fd5bfb5,0xbffb3fb5,0x3f8e3fb5,0x3ec8bfb5,0xbffb3f44,0xbf8e3fed,0xbec8bfed,0xbfd53f44,0x3ff50000,0x3f710000,0xbf154000,0xbfe24000,
0xbfa2bf8e,0x3fffbfd5,0x3fc6bfd5,0xbe493f8e,0x3e493fed,0x3fa2bfed,0xbfff3f44,0x3fc6bf44,0x3f71bffb,0xbf15bec8,0x3fe23ec8,0x3ff5bffb,
0xbf444000,0xbfed4000,0xbfed0000,0xbf440000,0x3fedbfb5,0xbf443fb5,0x3f443fb5,0xbfed3fb5,0xbfed0000,0x3f440000,0x3f44c000,0xbfed4000,
0x3f443fb5,0x3fedbfb5,0xbfed3fb5,0xbf443fb5,0xbfe20000,0xbf150000,0x3f71c000,0x3ff5c000,0x3e493fd5,0xbfc63f8e,0xbfff3f8e,0x3fa2bfd5,
0x3fc6bfed,0xbfff3fed,0x3fa23f44,0x3e49bf44,0xbff53ec8,0xbfe23ffb,0x3f15bffb,0xbf713ec8,0x3f8ec000,0x3ffbc000,0x3fd50000,0x3ec80000,
0xbffb3f44,0x3fd5bfed,0x3ec8bfed,0x3f8ebf44,0x3ec83fb5,0x3f8ebfb5,0xbffb3fb5,0x3fd5bfb5,0x3fd5bfed,0x3ec8bf44,0x3f8e3f44,0x3ffbbfed,
0x3fc60000,0x3e490000,0xbfa24000,0xbfff4000,0x3f71bffb,0x3f15bec8,0x3fe2bec8,0xbff53ffb,0xbff53f44,0x3f71bf44,0x3f15bfed,0xbfe23fed,
0xbe493fd5,0x3fa2bf8e,0xbfff3f8e,0xbfc63fd5,0xc0004000,0xbfb54000,0x0,0x3fb50000,0xc0004000,0x3fb50000,0x0,0x3fb5c000,
0xc0004000,0x3fb5c000,0x0,0xbfb50000,0xc0004000,0xbfb50000,0x0,0xbfb54000,0x3e490000,0x3fc60000,0x3fffc000,0x3fa2c000,
0x3f15bec8,0x3f71bffb,0x3ff5bffb,0xbfe23ec8,0x3f71bf44,0xbff53f44,0x3fe2bfed,0xbf153fed,0x3fa2bf8e,0xbe493fd5,0x3fc6bfd5,0x3fffbf8e,
0x3ffbc000,0x3f8ec000,0xbec80000,0xbfd50000,0x3fd5bfed,0xbffb3f44,0xbf8e3f44,0xbec83fed,0x3f8ebfb5,0x3ec83fb5,0xbfd53fb5,0x3ffbbfb5,
0x3ec8bf44,0x3fd5bfed,0xbffb3fed,0xbf8ebf44,0xbf150000,0xbfe20000,0xbff54000,0xbf714000,0xbfc63f8e,0x3e493fd5,0xbfa23fd5,0x3fffbf8e,
0xbfff3fed,0x3fc6bfed,0xbe493f44,0xbfa2bf44,0xbfe23ffb,0xbff53ec8,0x3f71bec8,0xbf153ffb,0xbfed4000,0xbf444000,0x3f440000,0x3fed0000,
0xbf443fb5,0x3fedbfb5,0x3fedbfb5,0xbf44bfb5,0x3f440000,0xbfed0000,0x3fedc000,0xbf444000,0x3fedbfb5,0x3f443fb5,0x3f44bfb5,0x3fedbfb5,
0x3f710000,0x3ff50000,0x3fe2c000,0x3f15c000,0x3fffbfd5,0xbfa2bf8e,0x3e49bf8e,0xbfc63fd5,0x3fa2bfed,0x3e493fed,0xbfc63f44,0x3fffbf44,
0xbf15bec8,0x3f71bffb,0xbff53ffb,0xbfe2bec8,0x3fd5c000,0x3ec8c000,0xbf8e0000,0xbffb0000,0xbec8bf44,0xbf8e3fed,0xbffb3fed,0x3fd53f44,
0xbffb3fb5,0x3fd5bfb5,0xbec83fb5,0xbf8ebfb5,0xbf8e3fed,0xbffb3f44,0x3fd5bf44,0x3ec83fed,0xbfa20000,0xbfff0000,0xbfc64000,0xbe494000,
0xbfe23ffb,0x3ff53ec8,0x3f713ec8,0x3f15bffb,0x3f153f44,0xbfe2bf44,0x3ff5bfed,0xbf713fed,0x3fffbfd5,0x3fc63f8e,0xbe49bf8e,0x3fa2bfd5,
0x4000,0x3fb54000,0x40000000,0x3fb50000,0xc000,0xbfb50000,0xc0000000,0x3fb54000,0x4000,0xbfb5c000,0x40000000,0xbfb50000,
0xc000,0x3fb50000,0xc0000000,0xbfb5c000,0x3fff0000,0x3fa20000,0xbe49c000,0xbfc6c000,0xbff53ec8,0x3fe23ffb,0x3f153ffb,0x3f71bec8,
0x3fe2bf44,0xbf153f44,0xbf71bfed,0x3ff53fed,0xbfc63f8e,0xbfffbfd5,0x3fa23fd5,0xbe493f8e,0xbec8c000,0xbfd5c000,0xbffb0000,0xbf8e0000,
0x3f8e3fed,0x3ec8bf44,0x3fd5bf44,0xbffbbfed,0xbfd5bfb5,0x3ffb3fb5,0xbf8e3fb5,0xbec8bfb5,0x3ffb3f44,0x3f8e3fed,0x3ec8bfed,0x3fd53f44,
0xbff50000,0xbf710000,0x3f154000,0x3fe24000,0x3fa2bf8e,0xbfffbfd5,0xbfc6bfd5,0x3e493f8e,0xbe493fed,0xbfa2bfed,0x3fff3f44,0xbfc6bf44,
0xbf71bffb,0x3f15bec8,0xbfe23ec8,0xbff5bffb,0x3f444000,0x3fed4000,0x3fed0000,0x3f440000,0xbfedbfb5,0x3f443fb5,0xbf443fb5,0x3fed3fb5,
0x3fed0000,0xbf440000,0xbf44c000,0x3fed4000,0xbf443fb5,0xbfedbfb5,0x3fed3fb5,0x3f443fb5,0x3fe20000,0x3f150000,0xbf71c000,0xbff5c000,
0xbe493fd5,0x3fc63f8e,0x3fff3f8e,0xbfa2bfd5,0xbfc6bfed,0x3fff3fed,0xbfa23f44,0xbe49bf44,0x3ff53ec8,0x3fe23ffb,0xbf15bffb,0x3f713ec8,
0xbf8ec000,0xbffbc000,0xbfd50000,0xbec80000,0x3ffb3f44,0xbfd5bfed,0xbec8bfed,0xbf8ebf44,0xbec83fb5,0xbf8ebfb5,0x3ffb3fb5,0xbfd5bfb5,
0xbfd5bfed,0xbec8bf44,0xbf8e3f44,0xbffbbfed,0xbfc60000,0xbe490000,0x3fa24000,0x3fff4000,0xbf71bffb,0xbf15bec8,0xbfe2bec8,0x3ff53ffb,
0x3ff53f44,0xbf71bf44,0xbf15bfed,0x3fe23fed,0x3e493fd5,0xbfa2bf8e,0x3fff3f8e,0x3fc63fd5,0x40004000,0x3fb54000,0x0,0xbfb50000,
0x40004000,0xbfb50000,0x0,0xbfb5c000,0x40004000,0xbfb5c000,0x0,0x3fb50000,0x40004000,0x3fb50000,0x0,0x3fb54000,
0xbfc6bfb5,0xbfffbfb5,0xbfa2bfb5,0x3e49bfb5,0xbfe2bfd5,0x3f15bf8e,0xbf71bf8e,0x3ff53fd5,0xbff5bfed,0x3fe23fed,0xbf15bf44,0xbf713f44,
0xbfffbffb,0xbfa23ec8,0xbe49bec8,0xbfc6bffb,0x3ec80000,0x3fd50000,0x3ffb4000,0x3f8e4000,0x3f8e3f44,0x3ec83fed,0x3fd53fed,0xbffbbf44,
0x3fd53fb5,0xbffbbfb5,0x3f8e3fb5,0x3ec8bfb5,0x3ffb3fed,0x3f8ebf44,0x3ec83f44,0x3fd53fed,0x3f713fb5,0xbf153fb5,0xbfe2bfb5,0xbff5bfb5,
0xbe493ec8,0xbfa2bffb,0xbfffbffb,0x3fc6bec8,0xbfa2bf44,0x3fff3f44,0xbfc6bfed,0x3e493fed,0xbff5bfd5,0xbf713f8e,0xbf15bf8e,0xbfe2bfd5,
0xbfedc000,0xbf44c000,0x3f440000,0x3fed0000,0xbf44bfb5,0x3fed3fb5,0x3fed3fb5,0xbf443fb5,0x3f440000,0xbfed0000,0x3fed4000,0xbf44c000,
0x3fed3fb5,0x3f44bfb5,0x3f443fb5,0x3fed3fb5,0x3ff53fb5,0x3fe23fb5,0x3f153fb5,0xbf713fb5,0x3fc63ffb,0xbfffbec8,0xbfa2bec8,0xbe49bffb,
0xbe493f44,0x3fc6bf44,0xbfffbfed,0x3fa23fed,0xbfe2bf8e,0xbf153fd5,0xbf71bfd5,0xbff5bf8e,0xbf8e0000,0xbffb0000,0xbfd5c000,0xbec8c000,
0xbffbbfed,0x3fd5bf44,0x3ec8bf44,0x3f8e3fed,0xbec8bfb5,0xbf8e3fb5,0x3ffb3fb5,0xbfd5bfb5,0x3fd53f44,0x3ec8bfed,0x3f8e3fed,0x3ffb3f44,
0xbe49bfb5,0x3fa2bfb5,0x3fff3fb5,0x3fc63fb5,0x3ff53f8e,0xbf713fd5,0x3f153fd5,0xbfe2bf8e,0x3f713fed,0x3f15bfed,0xbfe2bf44,0x3ff53f44,
0xbfc6bec8,0xbe493ffb,0xbfa2bffb,0xbfffbec8,0x4000,0xbfb54000,0xc0000000,0xbfb50000,0xc000,0x3fb50000,0x40000000,0xbfb54000,
0x4000,0x3fb5c000,0xc0000000,0x3fb50000,0xc000,0xbfb50000,0x40000000,0x3fb5c000,0xbfa2bfb5,0x3e49bfb5,0x3fc6bfb5,0x3fffbfb5,
0x3f713fd5,0xbff53f8e,0xbfe23f8e,0x3f15bfd5,0xbf15bfed,0xbf713fed,0x3ff5bf44,0xbfe23f44,0x3e493ffb,0x3fc6bec8,0xbfff3ec8,0xbfa23ffb,
0x3ffb0000,0x3f8e0000,0xbec84000,0xbfd54000,0xbfd5bf44,0x3ffbbfed,0x3f8ebfed,0x3ec83f44,0x3f8e3fb5,0x3ec8bfb5,0xbfd53fb5,0x3ffbbfb5,
0xbec8bfed,0xbfd53f44,0x3ffbbf44,0x3f8ebfed,0xbfe23fb5,0xbff53fb5,0xbf71bfb5,0x3f15bfb5,0x3fffbec8,0xbfc63ffb,0xbe493ffb,0xbfa23ec8,
0xbfc6bf44,0x3e493f44,0x3fa2bfed,0xbfff3fed,0x3f153fd5,0x3fe2bf8e,0xbff53f8e,0xbf713fd5,0x3f44c000,0x3fedc000,0x3fed0000,0x3f440000,
0xbfed3fb5,0x3f44bfb5,0xbf44bfb5,0x3fedbfb5,0x3fed0000,0xbf440000,0xbf444000,0x3fedc000,0xbf44bfb5,0xbfed3fb5,0x3fedbfb5,0x3f44bfb5,
0x3f153fb5,0xbf713fb5,0xbff53fb5,0xbfe23fb5,0x3fa2bffb,0x3e493ec8,0x3fc63ec8,0xbfff3ffb,0xbfff3f44,0x3fa2bf44,0x3e49bfed,0xbfc63fed,
0x3f713f8e,0x3ff5bfd5,0xbfe23fd5,0xbf153f8e,0xbfd50000,0xbec80000,0x3f8ec000,0x3ffbc000,0xbec83fed,0xbf8e3f44,0xbffb3f44,0x3fd5bfed,
0x3ffbbfb5,0xbfd53fb5,0x3ec83fb5,0x3f8ebfb5,0xbf8ebf44,0xbffb3fed,0x3fd5bfed,0x3ec8bf44,0x3fffbfb5,0x3fc6bfb5,0x3e493fb5,0xbfa23fb5,
0xbf15bf8e,0x3fe2bfd5,0x3ff5bfd5,0xbf713f8e,0xbfe23fed,0x3ff5bfed,0xbf71bf44,0xbf153f44,0x3fa23ec8,0x3fffbffb,0xbfc63ffb,0xbe493ec8,
0xc0004000,0xbfb54000,0x0,0x3fb50000,0xc0004000,0x3fb50000,0x0,0x3fb5c000,0xc0004000,0x3fb5c000,0x0,0xbfb50000,
0xc0004000,0xbfb50000,0x0,0xbfb54000,0x3fc6bfb5,0x3fffbfb5,0x3fa2bfb5,0xbe49bfb5,0x3fe2bfd5,0xbf15bf8e,0x3f71bf8e,0xbff53fd5,
0x3ff5bfed,0xbfe23fed,0x3f15bf44,0x3f713f44,0x3fffbffb,0x3fa23ec8,0x3e49bec8,0x3fc6bffb,0xbec80000,0xbfd50000,0xbffb4000,0xbf8e4000,
0xbf8e3f44,0xbec83fed,0xbfd53fed,0x3ffbbf44,0xbfd53fb5,0x3ffbbfb5,0xbf8e3fb5,0xbec8bfb5,0xbffb3fed,0xbf8ebf44,0xbec83f44,0xbfd53fed,
0xbf713fb5,0x3f153fb5,0x3fe2bfb5,0x3ff5bfb5,0x3e493ec8,0x3fa2bffb,0x3fffbffb,0xbfc6bec8,0x3fa2bf44,0xbfff3f44,0x3fc6bfed,0xbe493fed,
0x3ff5bfd5,0x3f713f8e,0x3f15bf8e,0x3fe2bfd5,0x3fedc000,0x3f44c000,0xbf440000,0xbfed0000,0x3f44bfb5,0xbfed3fb5,0xbfed3fb5,0x3f443fb5,
0xbf440000,0x3fed0000,0xbfed4000,0x3f44c000,0xbfed3fb5,0xbf44bfb5,0xbf443fb5,0xbfed3fb5,0xbff53fb5,0xbfe23fb5,0xbf153fb5,0x3f713fb5,
0xbfc63ffb,0x3fffbec8,0x3fa2bec8,0x3e49bffb,0x3e493f44,0xbfc6bf44,0x3fffbfed,0xbfa23fed,0x3fe2bf8e,0x3f153fd5,0x3f71bfd5,0x3ff5bf8e,
0x3f8e0000,0x3ffb0000,0x3fd5c000,0x3ec8c000,0x3ffbbfed,0xbfd5bf44,0xbec8bf44,0xbf8e3fed,0x3ec8bfb5,0x3f8e3fb5,0xbffb3fb5,0x3fd5bfb5,
0xbfd53f44,0xbec8bfed,0xbf8e3fed,0xbffb3f44,0x3e49bfb5,0xbfa2bfb5,0xbfff3fb5,0xbfc63fb5,0xbff53f8e,0x3f713fd5,0xbf153fd5,0x3fe2bf8e,
0xbf713fed,0xbf15bfed,0x3fe2bf44,0xbff53f44,0x3fc6bec8,0x3e493ffb,0x3fa2bffb,0x3fffbec8,0x4000,0x3fb54000,0x40000000,0x3fb50000,
0xc000,0xbfb50000,0xc0000000,0x3fb54000,0x4000,0xbfb5c000,0x40000000,0xbfb50000,0xc000,0x3fb50000,0xc0000000,0xbfb5c000,
0x3fa2bfb5,0xbe49bfb5,0xbfc6bfb5,0xbfffbfb5,0xbf713fd5,0x3ff53f8e,0x3fe23f8e,0xbf15bfd5,0x3f15bfed,0x3f713fed,0xbff5bf44,0x3fe23f44,
0xbe493ffb,0xbfc6bec8,0x3fff3ec8,0x3fa23ffb,0xbffb0000,0xbf8e0000,0x3ec84000,0x3fd54000,0x3fd5bf44,0xbffbbfed,0xbf8ebfed,0xbec83f44,
0xbf8e3fb5,0xbec8bfb5,0x3fd53fb5,0xbffbbfb5,0x3ec8bfed,0x3fd53f44,0xbffbbf44,0xbf8ebfed,0x3fe23fb5,0x3ff53fb5,0x3f71bfb5,0xbf15bfb5,
0xbfffbec8,0x3fc63ffb,0x3e493ffb,0x3fa23ec8,0x3fc6bf44,0xbe493f44,0xbfa2bfed,0x3fff3fed,0xbf153fd5,0xbfe2bf8e,0x3ff53f8e,0x3f713fd5,
0xbf44c000,0xbfedc000,0xbfed0000,0xbf440000,0x3fed3fb5,0xbf44bfb5,0x3f44bfb5,0xbfedbfb5,0xbfed0000,0x3f440000,0x3f444000,0xbfedc000,
0x3f44bfb5,0x3fed3fb5,0xbfedbfb5,0xbf44bfb5,0xbf153fb5,0x3f713fb5,0x3ff53fb5,0x3fe23fb5,0xbfa2bffb,0xbe493ec8,0xbfc63ec8,0x3fff3ffb,
0x3fff3f44,0xbfa2bf44,0xbe49bfed,0x3fc63fed,0xbf713f8e,0xbff5bfd5,0x3fe23fd5,0x3f153f8e,0x3fd50000,0x3ec80000,0xbf8ec000,0xbffbc000,
0x3ec83fed,0x3f8e3f44,0x3ffb3f44,0xbfd5bfed,0xbffbbfb5,0x3fd53fb5,0xbec83fb5,0xbf8ebfb5,0x3f8ebf44,0x3ffb3fed,0xbfd5bfed,0xbec8bf44,
0xbfffbfb5,0xbfc6bfb5,0xbe493fb5,0x3fa23fb5,0x3f15bf8e,0xbfe2bfd5,0xbff5bfd5,0x3f713f8e,0x3fe23fed,0xbff5bfed,0x3f71bf44,0x3f153f44,
0xbfa23ec8,0xbfffbffb,0x3fc63ffb,0x3e493ec8,0x80003f80,0x3f800000,0x80003f80,0x3f800000,0x80003f80,0x3f800000,0x80003f80,0x3f800000,
0x80003f80,0x3f800000,0x80003f80,0x3f800000,0x80003f80,0x3f800000,0x80003f80,0x3f800000,0x80003f80,0x3f800000,0x8000bf80,0xbf800000,
0x3f353f35,0x3f35bf35,0xbf35bf35,0xbf353f35,0x3f800000,0xbf80,0xbf800000,0x3f80,0x3f35bf35,0xbf35bf35,0xbf353f35,0x3f353f35,
0x80003f80,0x3f800000,0x80003f80,0x3f800000,0x3f800000,0xbf80,0x3f800000,0xbf80,0x8000bf80,0xbf800000,0x8000bf80,0xbf800000,
0xbf800000,0x3f80,0xbf800000,0x3f80,0x80003f80,0x3f800000,0x8000bf80,0xbf800000,0x3f35bf35,0xbf35bf35,0xbf353f35,0x3f353f35,
0xbf800000,0x3f80,0x3f800000,0xbf80,0x3f353f35,0x3f35bf35,0xbf35bf35,0xbf353f35,0x80003f80,0x3f800000,0x80003f80,0x3f800000,
0x8000bf80,0xbf800000,0x8000bf80,0xbf800000,0x80003f80,0x3f800000,0x80003f80,0x3f800000,0x8000bf80,0xbf800000,0x8000bf80,0xbf800000,
0x80003f80,0x3f800000,0x8000bf80,0xbf800000,0xbf35bf35,0xbf353f35,0x3f353f35,0x3f35bf35,0x3f800000,0xbf80,0xbf800000,0x3f80,
0xbf353f35,0x3f353f35,0x3f35bf35,0xbf35bf35,0x80003f80,0x3f800000,0x80003f80,0x3f800000,0xbf800000,0x3f80,0xbf800000,0x3f80,
0x8000bf80,0xbf800000,0x8000bf80,0xbf800000,0x3f800000,0xbf80,0x3f800000,0xbf80,0x80003f80,0x3f800000,0x8000bf80,0xbf800000,
0xbf353f35,0x3f353f35,0x3f35bf35,0xbf35bf35,0xbf800000,0x3f80,0x3f800000,0xbf80,0xbf35bf35,0xbf353f35,0x3f353f35,0x3f35bf35,
0x3f803f80,0x80008000,0x80008000,0xbf80bf80,0x3f803f80,0x80008000,0x80008000,0xbf80bf80,0x3f803f80,0x80008000,0x80008000,0xbf80bf80,
0x3f803f80,0x80008000,0x80008000,0xbf80bf80,0x3f353f80,0x3f358000,0x3f358000,0xbf35bf80,0xbf350000,0x3f353f80,0x3f353f80,0x3f358000,
0xbf35bf80,0xbf358000,0xbf358000,0x3f353f80,0x3f350000,0xbf35bf80,0xbf35bf80,0xbf358000,0x3f80,0x3f808000,0x3f808000,0x8000bf80,
0xbf80,0xbf808000,0xbf808000,0x80003f80,0x3f80,0x3f808000,0x3f808000,0x8000bf80,0xbf80,0xbf808000,0xbf808000,0x80003f80,
0xbf353f80,0x3f358000,0x3f358000,0x3f35bf80,0x3f350000,0x3f35bf80,0x3f35bf80,0xbf358000,0x3f35bf80,0xbf358000,0xbf358000,0xbf353f80,
0xbf350000,0xbf353f80,0xbf353f80,0x3f358000,0xbf803f80,0x80008000,0x80008000,0x3f80bf80,0xbf803f80,0x80008000,0x80008000,0x3f80bf80,
0xbf803f80,0x80008000,0x80008000,0x3f80bf80,0xbf803f80,0x80008000,0x80008000,0x3f80bf80,0xbf353f80,0xbf358000,0xbf358000,0x3f35bf80,
0x3f350000,0xbf353f80,0xbf353f80,0xbf358000,0x3f35bf80,0x3f358000,0x3f358000,0xbf353f80,0xbf350000,0x3f35bf80,0x3f35bf80,0x3f358000,
0x3f80,0xbf808000,0xbf808000,0x8000bf80,0xbf80,0x3f808000,0x3f808000,0x80003f80,0x3f80,0xbf808000,0xbf808000,0x8000bf80,
0xbf80,0x3f808000,0x3f808000,0x80003f80,0x3f353f80,0xbf358000,0xbf358000,0xbf35bf80,0xbf350000,0xbf35bf80,0xbf35bf80,0x3f358000,
0xbf35bf80,0x3f358000,0x3f358000,0x3f353f80,0x3f350000,0x3f353f80,0x3f353f80,0xbf358000,0x3f800000,0x0,0x3f800000,0x0,
0x3f800000,0x0,0x3f800000,0x0,0x3f800000,0x0,0x3f800000,0x0,0x3f800000,0x0,0x3f800000,0x0,
0x3f800000,0x0,0x3f7fb10f,0xbd48fb30,0x3f7ec46d,0xbdc8bd36,0x3f7d3aac,0xbe164083,0x3f7b14be,0xbe47c5c2,0x3f7853f8,0xbe78cfcc,
0x3f74fa0b,0xbe94a031,0x3f710908,0xbeac7cd4,0x3f800000,0x0,0x3f7ec46d,0xbdc8bd36,0x3f7b14be,0xbe47c5c2,0x3f74fa0b,0xbe94a031,
0x3f6c835e,0xbec3ef15,0x3f61c598,0xbef15aea,0x3f54db31,0xbf0e39da,0x3f45e403,0xbf226799,0x3f800000,0x0,0x3f7d3aac,0xbe164083,
0x3f74fa0b,0xbe94a031,0x3f676bd8,0xbedae880,0x3f54db31,0xbf0e39da,0x3f3daef9,0xbf2beb4a,0x3f226799,0xbf45e403,0x3f039c3d,0xbf5b941a,
0x3f800000,0x0,0x3f7b14be,0xbe47c5c2,0x3f6c835e,0xbec3ef15,0x3f54db31,0xbf0e39da,0x3f3504f3,0xbf3504f3,0x3f0e39da,0xbf54db31,
0x3ec3ef15,0xbf6c835e,0x3e47c5c2,0xbf7b14be,0x3f800000,0x0,0x3f7853f8,0xbe78cfcc,0x3f61c598,0xbef15aea,0x3f3daef9,0xbf2beb4a,
0x3f0e39da,0xbf54db31,0x3eac7cd4,0xbf710908,0x3dc8bd36,0xbf7ec46d,0xbe164083,0xbf7d3aac,0x3f800000,0x0,0x3f74fa0b,0xbe94a031,
0x3f54db31,0xbf0e39da,0x3f226799,0xbf45e403,0x3ec3ef15,0xbf6c835e,0x3dc8bd36,0xbf7ec46d,0xbe47c5c2,0xbf7b14be,0xbef15aea,0xbf61c598,
0x3f800000,0x0,0x3f710908,0xbeac7cd4,0x3f45e403,0xbf226799,0x3f039c3d,0xbf5b941a,0x3e47c5c2,0xbf7b14be,0xbe164083,0xbf7d3aac,
0xbef15aea,0xbf61c598,0xbf3daef9,0xbf2beb4a,0x3f800000,0x0,0x3f800000,0x0,0x3f800000,0x0,0x3f800000,0x0,
0x3f800000,0x0,0x3f800000,0x0,0x3f800000,0x0,0x3f800000,0x0,0x3f6c835e,0xbec3ef15,0x3f676bd8,0xbedae880,
0x3f61c598,0xbef15aea,0x3f5b941a,0xbf039c3d,0x3f54db31,0xbf0e39da,0x3f4d9f02,0xbf187fc0,0x3f45e403,0xbf226799,0x3f3daef9,0xbf2beb4a,
0x3f3504f3,0xbf3504f3,0x3f226799,0xbf45e403,0x3f0e39da,0xbf54db31,0x3ef15aea,0xbf61c598,0x3ec3ef15,0xbf6c835e,0x3e94a031,0xbf74fa0b,
0x3e47c5c2,0xbf7b14be,0x3dc8bd36,0xbf7ec46d,0x3ec3ef15,0xbf6c835e,0x3e78cfcc,0xbf7853f8,0x3dc8bd36,0xbf7ec46d,0xbd48fb30,0xbf7fb10f,
0xbe47c5c2,0xbf7b14be,0xbeac7cd4,0xbf710908,0xbef15aea,0xbf61c598,0xbf187fc0,0xbf4d9f02,0x0,0xbf800000,0xbe47c5c2,0xbf7b14be,
0xbec3ef15,0xbf6c835e,0xbf0e39da,0xbf54db31,0xbf3504f3,0xbf3504f3,0xbf54db31,0xbf0e39da,0xbf6c835e,0xbec3ef15,0xbf7b14be,0xbe47c5c2,
0xbec3ef15,0xbf6c835e,0xbf187fc0,0xbf4d9f02,0xbf45e403,0xbf226799,0xbf676bd8,0xbedae880,0xbf7b14be,0xbe47c5c2,0xbf7fb10f,0x3d48fb30,
0xbf74fa0b,0x3e94a031,0xbf5b941a,0x3f039c3d,0xbf3504f3,0xbf3504f3,0xbf61c598,0xbef15aea,0xbf7b14be,0xbe47c5c2,0xbf7ec46d,0x3dc8bd36,
0xbf6c835e,0x3ec3ef15,0xbf45e403,0x3f226799,0xbf0e39da,0x3f54db31,0xbe94a031,0x3f74fa0b,0xbf6c835e,0xbec3ef15,0xbf7fb10f,0xbd48fb30,
0xbf74fa0b,0x3e94a031,0xbf4d9f02,0x3f187fc0,0xbf0e39da,0x3f54db31,0xbe78cfcc,0x3f7853f8,0x3dc8bd36,0x3f7ec46d,0x3edae880,0x3f676bd8,
0x80003f80,0x3f800000,0x3f800000,0xbf80,0x3ec43f6d,0x3f6dbec4,0x3f6dbec4,0xbec4bf6d,0x3f353f35,0x3f35bf35,0x3f35bf35,0xbf35bf35,
0x3f6d3ec4,0x3ec4bf6d,0x3ec4bf6d,0xbf6dbec4,0x80003f80,0x3f800000,0xbf800000,0x3f80,0x3f6d3ec4,0x3ec4bf6d,0xbec43f6d,0x3f6d3ec4,
0x3f35bf35,0xbf35bf35,0x3f353f35,0x3f35bf35,0xbec4bf6d,0xbf6d3ec4,0x3f6dbec4,0xbec4bf6d,0x80003f80,0x3f800000,0x3f800000,0xbf80,
0x3f6dbec4,0xbec4bf6d,0xbec4bf6d,0xbf6d3ec4,0xbf35bf35,0xbf353f35,0xbf353f35,0x3f353f35,0xbec43f6d,0x3f6d3ec4,0x3f6d3ec4,0x3ec4bf6d,
0x80003f80,0x3f800000,0xbf800000,0x3f80,0x3ec4bf6d,0xbf6dbec4,0x3f6d3ec4,0x3ec4bf6d,0xbf353f35,0x3f353f35,0xbf35bf35,0xbf353f35,
0x3f6dbec4,0xbec4bf6d,0x3ec43f6d,0x3f6dbec4,0x80003f80,0x3f800000,0x3f800000,0xbf80,0xbec4bf6d,0xbf6d3ec4,0xbf6d3ec4,0x3ec43f6d,
0x3f353f35,0x3f35bf35,0x3f35bf35,0xbf35bf35,0xbf6dbec4,0xbec43f6d,0xbec43f6d,0x3f6d3ec4,0x80003f80,0x3f800000,0xbf800000,0x3f80,
0xbf6dbec4,0xbec43f6d,0x3ec4bf6d,0xbf6dbec4,0x3f35bf35,0xbf35bf35,0x3f353f35,0x3f35bf35,0x3ec43f6d,0x3f6dbec4,0xbf6d3ec4,0x3ec43f6d,
0x80003f80,0x3f800000,0x3f800000,0xbf80,0xbf6d3ec4,0x3ec43f6d,0x3ec43f6d,0x3f6dbec4,0xbf35bf35,0xbf353f35,0xbf353f35,0x3f353f35,
0x3ec4bf6d,0xbf6dbec4,0xbf6dbec4,0xbec43f6d,0x80003f80,0x3f800000,0xbf800000,0x3f80,0xbec43f6d,0x3f6d3ec4,0xbf6dbec4,0xbec43f6d,
0xbf353f35,0x3f353f35,0xbf35bf35,0xbf353f35,0xbf6d3ec4,0x3ec43f6d,0xbec4bf6d,0xbf6d3ec4,0x3f803f80,0x80008000,0x80008000,0xbf80bf80,
0x3f803f80,0x80008000,0x80008000,0xbf80bf80,0x3f803f80,0x80008000,0x80008000,0xbf80bf80,0x3f803f80,0x80008000,0x80008000,0xbf80bf80,
0x3ec43f6d,0x3f6d3ec4,0x3f6d3ec4,0xbec4bf6d,0xbf6dbec4,0x3ec43f6d,0x3ec43f6d,0x3f6d3ec4,0xbec4bf6d,0xbf6dbec4,0xbf6dbec4,0x3ec43f6d,
0x3f6d3ec4,0xbec4bf6d,0xbec4bf6d,0xbf6dbec4,0xbf353f35,0x3f353f35,0x3f353f35,0x3f35bf35,0x3f35bf35,0xbf35bf35,0xbf35bf35,0xbf353f35,
0xbf353f35,0x3f353f35,0x3f353f35,0x3f35bf35,0x3f35bf35,0xbf35bf35,0xbf35bf35,0xbf353f35,0xbf6d3ec4,0xbec43f6d,0xbec43f6d,0x3f6dbec4,
0xbec43f6d,0x3f6dbec4,0x3f6dbec4,0x3ec4bf6d,0x3f6dbec4,0x3ec4bf6d,0x3ec4bf6d,0xbf6d3ec4,0x3ec4bf6d,0xbf6d3ec4,0xbf6d3ec4,0xbec43f6d,
0x0,0xbf803f80,0xbf803f80,0x80008000,0x0,0xbf803f80,0xbf803f80,0x80008000,0x0,0xbf803f80,0xbf803f80,0x80008000,
0x0,0xbf803f80,0xbf803f80,0x80008000,0x3f6dbec4,0xbec43f6d,0xbec43f6d,0xbf6d3ec4,0x3ec4bf6d,0x3f6dbec4,0x3f6dbec4,0xbec43f6d,
0xbf6d3ec4,0x3ec4bf6d,0x3ec4bf6d,0x3f6dbec4,0xbec43f6d,0xbf6d3ec4,0xbf6d3ec4,0x3ec4bf6d,0x3f35bf35,0x3f353f35,0x3f353f35,0xbf353f35,
0xbf353f35,0xbf35bf35,0xbf35bf35,0x3f35bf35,0x3f35bf35,0x3f353f35,0x3f353f35,0xbf353f35,0xbf353f35,0xbf35bf35,0xbf35bf35,0x3f35bf35,
0xbec4bf6d,0x3f6d3ec4,0x3f6d3ec4,0x3ec43f6d,0x3f6d3ec4,0x3ec43f6d,0x3ec43f6d,0xbf6dbec4,0x3ec43f6d,0xbf6dbec4,0xbf6dbec4,0xbec4bf6d,
0xbf6dbec4,0xbec4bf6d,0xbec4bf6d,0x3f6d3ec4,0x3f800000,0x0,0x3f7fec43,0xbcc90ab0,0x3f7fb10f,0xbd48fb30,0x3f7f4e6d,0xbd96a905,
0x3f7ec46d,0xbdc8bd36,0x3f7e1324,0xbdfab273,0x3f7d3aac,0xbe164083,0x3f7c3b28,0xbe2f10a2,0x3f800000,0x0,0x3f7f4e6d,0xbd96a905,
0x3f7d3aac,0xbe164083,0x3f79c79d,0xbe605c13,0x3f74fa0b,0xbe94a031,0x3f6ed89e,0xbeb8442a,0x3f676bd8,0xbedae880,0x3f5ebe05,0xbefc5d27,
0x3f800000,0x0,0x3f7e1324,0xbdfab273,0x3f7853f8,0xbe78cfcc,0x3f6ed89e,0xbeb8442a,0x3f61c598,0xbef15aea,0x3f514d3d,0xbf13682a,
0x3f3daef9,0xbf2beb4a,0x3f273656,0xbf41d870,0x3f800000,0x0,0x3f7c3b28,0xbe2f10a2,0x3f710908,0xbeac7cd4,0x3f5ebe05,0xbefc5d27,
0x3f45e403,0xbf226799,0x3f273656,0xbf41d870,0x3f039c3d,0xbf5b941a,0x3eb8442a,0xbf6ed89e,0x3f800000,0x0,0x3f79c79d,0xbe605c13,
0x3f676bd8,0xbedae880,0x3f49d112,0xbf1d7fd1,0x3f226799,0xbf45e403,0x3ee63375,0xbf64aa59,0x3e78cfcc,0xbf7853f8,0x3cc90ab0,0xbf7fec43,
0x3f800000,0x0,0x3f76ba07,0xbe888e93,0x3f5b941a,0xbf039c3d,0x3f3085bb,0xbf396842,0x3ef15aea,0xbf61c598,0x3e605c13,0xbf79c79d,
0xbd48fb30,0xbf7fb10f,0xbea09ae5,0xbf731447,0x3f800000,0x0,0x3f731447,0xbea09ae5,0x3f4d9f02,0xbf187fc0,0x3f13682a,0xbf514d3d,
0x3e94a031,0xbf74fa0b,0xbcc90ab0,0xbf7fec43,0xbeac7cd4,0xbf710908,0xbf1d7fd1,0xbf49d112,0x3f800000,0x0,0x3f6ed89e,0xbeb8442a,
0x3f3daef9,0xbf2beb4a,0x3ee63375,0xbf64aa59,0x3dc8bd36,0xbf7ec46d,0xbe888e93,0xbf76ba07,0xbf187fc0,0xbf4d9f02,0xbf584853,0xbf08f59b,
0x3f7b14be,0xbe47c5c2,0x3f79c79d,0xbe605c13,0x3f7853f8,0xbe78cfcc,0x3f76ba07,0xbe888e93,0x3f74fa0b,0xbe94a031,0x3f731447,0xbea09ae5,
0x3f710908,0xbeac7cd4,0x3f6ed89e,0xbeb8442a,0x3f54db31,0xbf0e39da,0x3f49d112,0xbf1d7fd1,0x3f3daef9,0xbf2beb4a,0x3f3085bb,0xbf396842,
0x3f226799,0xbf45e403,0x3f13682a,0xbf514d3d,0x3f039c3d,0xbf5b941a,0x3ee63375,0xbf64aa59,0x3f0e39da,0xbf54db31,0x3ee63375,0xbf64aa59,
0x3eac7cd4,0xbf710908,0x3e605c13,0xbf79c79d,0x3dc8bd36,0xbf7ec46d,0xbcc90ab0,0xbf7fec43,0xbe164083,0xbf7d3aac,0xbe888e93,0xbf76ba07,
0x3e47c5c2,0xbf7b14be,0x3cc90ab0,0xbf7fec43,0xbe164083,0xbf7d3aac,0xbea09ae5,0xbf731447,0xbef15aea,0xbf61c598,0xbf1d7fd1,0xbf49d112,
0xbf3daef9,0xbf2beb4a,0xbf584853,0xbf08f59b,0xbe47c5c2,0xbf7b14be,0xbecf7bca,0xbf6a09a7,0xbf187fc0,0xbf4d9f02,0xbf41d870,0xbf273656,
0xbf61c598,0xbef15aea,0xbf76ba07,0xbe888e93,0xbf7fb10f,0xbd48fb30,0xbf7c3b28,0x3e2f10a2,0xbf0e39da,0xbf54db31,0xbf41d870,0xbf273656,
0xbf676bd8,0xbedae880,0xbf7c3b28,0xbe2f10a2,0xbf7ec46d,0x3dc8bd36,0xbf6ed89e,0x3eb8442a,0xbf4d9f02,0x3f187fc0,0xbf1d7fd1,0x3f49d112,
0xbf54db31,0xbf0e39da,0xbf76ba07,0xbe888e93,0xbf7fb10f,0x3d48fb30,0xbf6ed89e,0x3eb8442a,0xbf45e403,0x3f226799,0xbf08f59b,0x3f584853,
0xbe78cfcc,0x3f7853f8,0x3d96a905,0x3f7f4e6d,0xbf7b14be,0xbe47c5c2,0xbf7c3b28,0x3e2f10a2,0xbf5b941a,0x3f039c3d,0xbf1d7fd1,0x3f49d112,
0xbe94a031,0x3f74fa0b,0x3d96a905,0x3f7f4e6d,0x3edae880,0x3f676bd8,0x3f396842,0x3f3085bb,0x80003f80,0x80003f80,0x80003f80,0x80003f80,
0x80003f80,0x80003f80,0x80003f80,0x80003f80,0x80003f80,0x80003f80,0x80003f80,0x80003f80,0x80003f80,0x80003f80,0x80003f80,0x80003f80,
0x3f800000,0x3f800000,0x3f800000,0x3f800000,0x3f800000,0x3f800000,0x3f800000,0x3f800000,0x3f800000,0x3f800000,0x3f800000,0x3f800000,
0x3f800000,0x3f800000,0x3f800000,0x3f800000,0x80003f80,0x3f353f35,0x80003f80,0x3f353f35,0x3f800000,0x3f35bf35,0x3f800000,0x3f35bf35,
0x8000bf80,0xbf35bf35,0x8000bf80,0xbf35bf35,0xbf800000,0xbf353f35,0xbf800000,0xbf353f35,0x3f800000,0x3f35bf35,0x3f800000,0x3f35bf35,
0xbf80,0xbf35bf35,0xbf80,0xbf35bf35,0xbf800000,0xbf353f35,0xbf800000,0xbf353f35,0x3f80,0x3f353f35,0x3f80,0x3f353f35,
0x80003f80,0x3f800000,0x80003f80,0x3f800000,0x8000bf80,0xbf800000,0x8000bf80,0xbf800000,0x80003f80,0x3f800000,0x80003f80,0x3f800000,
0x8000bf80,0xbf800000,0x8000bf80,0xbf800000,0x3f800000,0xbf80,0x3f800000,0xbf80,0xbf800000,0x3f80,0xbf800000,0x3f80,
0x3f800000,0xbf80,0x3f800000,0xbf80,0xbf800000,0x3f80,0xbf800000,0x3f80,0x80003f80,0x3f35bf35,0x80003f80,0x3f35bf35,
0xbf800000,0x3f353f35,0xbf800000,0x3f353f35,0x8000bf80,0xbf353f35,0x8000bf80,0xbf353f35,0x3f800000,0xbf35bf35,0x3f800000,0xbf35bf35,
0x3f800000,0xbf35bf35,0x3f800000,0xbf35bf35,0x3f80,0x3f35bf35,0x3f80,0x3f35bf35,0xbf800000,0x3f353f35,0xbf800000,0x3f353f35,
0xbf80,0xbf353f35,0xbf80,0xbf353f35,0x80003f80,0x3ec43f6d,0x8000bf80,0xbec4bf6d,0x3f353f35,0x3f6d3ec4,0xbf35bf35,0xbf6dbec4,
0x3f800000,0x3f6dbec4,0xbf800000,0xbf6d3ec4,0x3f35bf35,0x3ec4bf6d,0xbf353f35,0xbec43f6d,0x3f800000,0x3f6dbec4,0xbf800000,0xbf6d3ec4,
0x3f35bf35,0x3ec4bf6d,0xbf353f35,0xbec43f6d,0xbf80,0xbec4bf6d,0x3f80,0x3ec43f6d,0xbf35bf35,0xbf6dbec4,0x3f353f35,0x3f6d3ec4,
0x80003f80,0x3f6d3ec4,0x8000bf80,0xbf6dbec4,0x3f35bf35,0xbec4bf6d,0xbf353f35,0x3ec43f6d,0xbf800000,0xbec43f6d,0x3f800000,0x3ec4bf6d,
0x3f353f35,0x3f6dbec4,0xbf35bf35,0xbf6d3ec4,0x3f800000,0x3ec4bf6d,0xbf800000,0xbec43f6d,0xbf35bf35,0xbf6d3ec4,0x3f353f35,0x3f6dbec4,
0x3f80,0x3f6d3ec4,0xbf80,0xbf6dbec4,0x3f35bf35,0xbec4bf6d,0xbf353f35,0x3ec43f6d,0x80003f80,0x3f6dbec4,0x8000bf80,0xbf6d3ec4,
0xbf35bf35,0xbec43f6d,0x3f353f35,0x3ec4bf6d,0x3f800000,0xbec4bf6d,0xbf800000,0x3ec43f6d,0xbf353f35,0x3f6d3ec4,0x3f35bf35,0xbf6dbec4,
0x3f800000,0xbec4bf6d,0xbf800000,0x3ec43f6d,0xbf353f35,0x3f6d3ec4,0x3f35bf35,0xbf6dbec4,0xbf80,0xbf6d3ec4,0x3f80,0x3f6dbec4,
0x3f353f35,0x3ec4bf6d,0xbf35bf35,0xbec43f6d,0x80003f80,0x3ec4bf6d,0x8000bf80,0xbec43f6d,0xbf353f35,0x3f6dbec4,0x3f35bf35,0xbf6d3ec4,
0xbf800000,0x3f6d3ec4,0x3f800000,0xbf6dbec4,0xbf35bf35,0x3ec43f6d,0x3f353f35,0xbec4bf6d,0x3f800000,0xbf6dbec4,0xbf800000,0x3f6d3ec4,
0x3f353f35,0xbec4bf6d,0xbf35bf35,0x3ec43f6d,0x3f80,0x3ec4bf6d,0xbf80,0xbec43f6d,0xbf353f35,0x3f6dbec4,0x3f35bf35,0xbf6d3ec4,
0x80003f80,0x8000bf80,0x80003f80,0x8000bf80,0x80003f80,0x8000bf80,0x80003f80,0x8000bf80,0x80003f80,0x8000bf80,0x80003f80,0x8000bf80,
0x80003f80,0x8000bf80,0x80003f80,0x8000bf80,0x3f800000,0xbf800000,0x3f800000,0xbf800000,0x3f800000,0xbf800000,0x3f800000,0xbf800000,
0x3f800000,0xbf800000,0x3f800000,0xbf800000,0x3f800000,0xbf800000,0x3f800000,0xbf800000,0x80003f80,0xbf35bf35,0x80003f80,0xbf35bf35,
0x3f800000,0xbf353f35,0x3f800000,0xbf353f35,0x8000bf80,0x3f353f35,0x8000bf80,0x3f353f35,0xbf800000,0x3f35bf35,0xbf800000,0x3f35bf35,
0x3f800000,0xbf353f35,0x3f800000,0xbf353f35,0xbf80,0x3f353f35,0xbf80,0x3f353f35,0xbf800000,0x3f35bf35,0xbf800000,0x3f35bf35,
0x3f80,0xbf35bf35,0x3f80,0xbf35bf35,0x80003f80,0xbf800000,0x80003f80,0xbf800000,0x8000bf80,0x3f800000,0x8000bf80,0x3f800000,
0x80003f80,0xbf800000,0x80003f80,0xbf800000,0x8000bf80,0x3f800000,0x8000bf80,0x3f800000,0x3f800000,0x3f80,0x3f800000,0x3f80,
0xbf800000,0xbf80,0xbf800000,0xbf80,0x3f800000,0x3f80,0x3f800000,0x3f80,0xbf800000,0xbf80,0xbf800000,0xbf80,
0x80003f80,0xbf353f35,0x80003f80,0xbf353f35,0xbf800000,0xbf35bf35,0xbf800000,0xbf35bf35,0x8000bf80,0x3f35bf35,0x8000bf80,0x3f35bf35,
0x3f800000,0x3f353f35,0x3f800000,0x3f353f35,0x3f800000,0x3f353f35,0x3f800000,0x3f353f35,0x3f80,0xbf353f35,0x3f80,0xbf353f35,
0xbf800000,0xbf35bf35,0xbf800000,0xbf35bf35,0xbf80,0x3f35bf35,0xbf80,0x3f35bf35,0x80003f80,0xbec4bf6d,0x8000bf80,0x3ec43f6d,
0x3f353f35,0xbf6dbec4,0xbf35bf35,0x3f6d3ec4,0x3f800000,0xbf6d3ec4,0xbf800000,0x3f6dbec4,0x3f35bf35,0xbec43f6d,0xbf353f35,0x3ec4bf6d,
0x3f800000,0xbf6d3ec4,0xbf800000,0x3f6dbec4,0x3f35bf35,0xbec43f6d,0xbf353f35,0x3ec4bf6d,0xbf80,0x3ec43f6d,0x3f80,0xbec4bf6d,
0xbf35bf35,0x3f6d3ec4,0x3f353f35,0xbf6dbec4,0x80003f80,0xbf6dbec4,0x8000bf80,0x3f6d3ec4,0x3f35bf35,0x3ec43f6d,0xbf353f35,0xbec4bf6d,
0xbf800000,0x3ec4bf6d,0x3f800000,0xbec43f6d,0x3f353f35,0xbf6d3ec4,0xbf35bf35,0x3f6dbec4,0x3f800000,0xbec43f6d,0xbf800000,0x3ec4bf6d,
0xbf35bf35,0x3f6dbec4,0x3f353f35,0xbf6d3ec4,0x3f80,0xbf6dbec4,0xbf80,0x3f6d3ec4,0x3f35bf35,0x3ec43f6d,0xbf353f35,0xbec4bf6d,
0x80003f80,0xbf6d3ec4,0x8000bf80,0x3f6dbec4,0xbf35bf35,0x3ec4bf6d,0x3f353f35,0xbec43f6d,0x3f800000,0x3ec43f6d,0xbf800000,0xbec4bf6d,
0xbf353f35,0xbf6dbec4,0x3f35bf35,0x3f6d3ec4,0x3f800000,0x3ec43f6d,0xbf800000,0xbec4bf6d,0xbf353f35,0xbf6dbec4,0x3f35bf35,0x3f6d3ec4,
0xbf80,0x3f6dbec4,0x3f80,0xbf6d3ec4,0x3f353f35,0xbec43f6d,0xbf35bf35,0x3ec4bf6d,0x80003f80,0xbec43f6d,0x8000bf80,0x3ec4bf6d,
0xbf353f35,0xbf6d3ec4,0x3f35bf35,0x3f6dbec4,0xbf800000,0xbf6dbec4,0x3f800000,0x3f6d3ec4,0xbf35bf35,0xbec4bf6d,0x3f353f35,0x3ec43f6d,
0x3f800000,0x3f6d3ec4,0xbf800000,0xbf6dbec4,0x3f353f35,0x3ec43f6d,0xbf35bf35,0xbec4bf6d,0x3f80,0xbec43f6d,0xbf80,0x3ec4bf6d,
0xbf353f35,0xbf6d3ec4,0x3f35bf35,0x3f6dbec4,
};
constexpr int TB_F = 0, TB_E = 512, TB_P2 = 1024;

enum { C_EP = 0, C_Z1 = 32, C_Z2 = 96, C_H3 = 128, C_U = 160, C_TOTAL = 256 };
struct Scratch {
  unsigned cnt[C_TOTAL];
  uint32_t moda[8 * 2 * D_];
  uint32_t mod[4 * D_ + 256];
  uint32_t z1[120 * 5120];
  uint32_t z2[128 * 4800];
  uint32_t x1[S_ * D_ / 2];
  uint8_t h3[32 * 18 * 4096];
  uint8_t u[72 * D_ * 128];
  uint4 part[128 * 1152];
};
__device__ __align__(1024) Scratch g_s;

#define PF2 8
#define PF2K 16
#define HOLDA 3
#define GOAT 1
#define HOLD1 0
#define XPOS 0
#define HW bulk_commit_wait
#define H3W 0
#define X1K 10
#define PEEK 1
#define H3G 2
#define MODBAR 1
#define NG1 2

#define FAILCNT(k) do {} while (0)
#define CK(k) do {} while (0)
#define CKX(k) do {} while (0)
#define TS(k) do {} while (0)
#define TSC(k) do {} while (0)
struct Maps { CUtensorMap w1a, w1b, w2, x1, out, z1, z2, h3[2], wf[4], wm; };
struct Params {
  const __nv_bfloat16 *x, *c, *wmod;
  Scratch* s;
  const uint4* tab;
  const __nv_bfloat16 *wr, *wi, *w1, *w2, *b1, *b2;
};

__device__ __forceinline__ uint32_t smem_u32(const void* p) { return (uint32_t)__cvta_generic_to_shared(p); }
__device__ __forceinline__ void mbar_init(uint32_t b, int c) { asm volatile("mbarrier.init.shared::cta.b64 [%0], %1;" ::"r"(b), "r"(c)); }
__device__ __forceinline__ void mbar_expect(uint32_t b, int bytes) { asm volatile("mbarrier.arrive.expect_tx.shared::cta.b64 _, [%0], %1;" ::"r"(b), "r"(bytes) : "memory"); }
__device__ __forceinline__ void mbar_arrive(uint32_t b) { asm volatile("mbarrier.arrive.shared::cta.b64 _, [%0];" ::"r"(b) : "memory"); }
#define MBAR_WAIT(SEM)                                                                                                         \
  asm volatile("{\n.reg .pred p;\n.reg .u32 it;\nmov.u32 it, 0;\nW:\nmbarrier.try_wait.parity" SEM ".shared::cta.b64 p, [%0], %1;\n" \
               "@p bra.uni D;\nadd.u32 it, it, 1;\nsetp.lt.u32 p, it, 0x400000;\n@p bra.uni W;\ntrap;\nD:\n}" ::"r"(b), "r"(ph) : "memory")
__device__ __forceinline__ void mbar_wait(uint32_t b, int ph) { MBAR_WAIT(""); }
__device__ __forceinline__ uint32_t mbar_test(uint32_t b, int ph) {
  uint32_t ok;
  asm volatile("{\n.reg .pred p;\nmbarrier.test_wait.parity.shared::cta.b64 p, [%1], %2;\nselp.u32 %0, 1, 0, p;\n}\n" : "=r"(ok) : "r"(b), "r"(ph) : "memory");
  return ok;
}
__device__ __forceinline__ void tma2d(uint32_t dst, const CUtensorMap* m, int c0, int c1, uint32_t bar) {
  asm volatile("cp.async.bulk.tensor.2d.shared::cluster.global.mbarrier::complete_tx::bytes [%0], [%1, {%3, %4}], [%2];" ::"r"(dst), "l"(m), "r"(bar), "r"(c0), "r"(c1) : "memory");
}
__device__ __forceinline__ uint64_t pol_ef() { uint64_t p; asm("createpolicy.fractional.L2::evict_first.b64 %0, 1.0;" : "=l"(p)); return p; }
__device__ __forceinline__ void tma3d_ef(uint32_t dst, const CUtensorMap* m, int c1, int c2, uint32_t bar) {
  asm volatile("cp.async.bulk.tensor.3d.shared::cluster.global.mbarrier::complete_tx::bytes.L2::cache_hint [%0], [%1, {%3, %4, %5}], [%2], %6;" ::"r"(dst), "l"(m), "r"(bar), "r"(0), "r"(c1), "r"(c2), "l"(pol_ef()) : "memory");
}
__device__ __forceinline__ void tma4d_ef(uint32_t dst, const CUtensorMap* m, int c1, int c2, int c3, uint32_t bar) {
  asm volatile("cp.async.bulk.tensor.4d.shared::cluster.global.mbarrier::complete_tx::bytes.L2::cache_hint [%0], [%1, {%3, %7, %4, %5}], [%2], %6;" ::"r"(dst), "l"(m), "r"(bar), "r"(0), "r"(c2), "r"(c3), "l"(pol_ef()), "r"(c1) : "memory");
}
__device__ __forceinline__ void bulk_ld(uint32_t dst, const void* src, int bytes, uint32_t bar) {
  asm volatile("cp.async.bulk.shared::cluster.global.mbarrier::complete_tx::bytes [%0], [%1], %2, [%3];" ::"r"(dst), "l"(src), "r"(bytes), "r"(bar) : "memory");
}
__device__ __forceinline__ void bulk_st(void* dst, uint32_t src, int bytes) {
  asm volatile("cp.async.bulk.global.shared::cta.bulk_group [%0], [%1], %2;" ::"l"(dst), "r"(src), "r"(bytes) : "memory");
}
__device__ __forceinline__ void tma_st2d(const CUtensorMap* m, uint32_t src, int c0, int c1) {
  asm volatile("cp.async.bulk.tensor.2d.global.shared::cta.bulk_group [%0, {%2, %3}], [%1];" ::"l"(m), "r"(src), "r"(c0), "r"(c1) : "memory");
}
__device__ __forceinline__ void tma_st3d(const CUtensorMap* m, uint32_t src, int c0, int c1, int c2) {
  asm volatile("cp.async.bulk.tensor.3d.global.shared::cta.bulk_group [%0, {%2, %3, %4}], [%1];" ::"l"(m), "r"(src), "r"(c0), "r"(c1), "r"(c2) : "memory");
}
__device__ __forceinline__ void bulk_commit_wait_read() {
  asm volatile("cp.async.bulk.commit_group;" ::: "memory");
  asm volatile("cp.async.bulk.wait_group.read 0;" ::: "memory");
}
__device__ __forceinline__ void bulk_commit_wait() {
  asm volatile("cp.async.bulk.commit_group;" ::: "memory");
  asm volatile("cp.async.bulk.wait_group 0;" ::: "memory");
}
__device__ __forceinline__ void prefetch_l2(const void* p, int bytes) {
  asm volatile("cp.async.bulk.prefetch.L2.global [%0], %1;" ::"l"(p), "r"(bytes) : "memory");
}
__device__ __forceinline__ void wg_fence() { asm volatile("wgmma.fence.sync.aligned;" ::: "memory"); }
__device__ __forceinline__ void wg_commit() { asm volatile("wgmma.commit_group.sync.aligned;" ::: "memory"); }
template <int N> __device__ __forceinline__ void wg_wait() { asm volatile("wgmma.wait_group.sync.aligned %0;" ::"n"(N) : "memory"); }
template <int N> __device__ __forceinline__ void reg_fence(float (&d)[N]) {
#pragma unroll
  for (int i = 0; i < N; i++) asm volatile("" : "+f"(d[i])::"memory");
}
__device__ __forceinline__ void fence_async_smem() { asm volatile("fence.proxy.async.shared::cta;" ::: "memory"); }
__device__ __forceinline__ void fence_async_glb() { asm volatile("fence.proxy.async.global;" ::: "memory"); }
__device__ __forceinline__ uint32_t ld_rlx(const void* p) { uint32_t v; asm volatile("ld.relaxed.gpu.global.b32 %0, [%1];" : "=r"(v) : "l"(p) : "memory"); return v; }
__device__ __forceinline__ uint2 ld_rlx2(const void* p) { uint2 v; asm volatile("ld.relaxed.gpu.global.v2.b32 {%0,%1}, [%2];" : "=r"(v.x), "=r"(v.y) : "l"(p) : "memory"); return v; }
__device__ __forceinline__ uint4 ld_rlx4(const void* p) { uint4 v; asm volatile("ld.relaxed.gpu.global.v4.b32 {%0,%1,%2,%3}, [%4];" : "=r"(v.x), "=r"(v.y), "=r"(v.z), "=r"(v.w) : "l"(p) : "memory"); return v; }
__device__ __forceinline__ uint32_t ld_nc(const void* p) { uint32_t v; asm volatile("ld.global.nc.L1::no_allocate.b32 %0, [%1];" : "=r"(v) : "l"(p) : "memory"); return v; }
__device__ __forceinline__ uint32_t lds(uint32_t a) { uint32_t v; asm volatile("ld.shared.b32 %0, [%1];" : "=r"(v) : "r"(a) : "memory"); return v; }
__device__ __forceinline__ uint2 lds2(uint32_t a) { uint2 v; asm volatile("ld.shared.v2.b32 {%0,%1}, [%2];" : "=r"(v.x), "=r"(v.y) : "r"(a) : "memory"); return v; }
__device__ __forceinline__ uint4 lds4(uint32_t a) { uint4 v; asm volatile("ld.shared.v4.b32 {%0,%1,%2,%3}, [%4];" : "=r"(v.x), "=r"(v.y), "=r"(v.z), "=r"(v.w) : "r"(a) : "memory"); return v; }
__device__ __forceinline__ float lds_bf(uint32_t a) { uint32_t v; asm volatile("ld.shared.u16 %0, [%1];" : "=r"(v) : "r"(a) : "memory"); return __uint_as_float(v << 16); }
__device__ __forceinline__ void sts(uint32_t a, uint32_t v) { asm volatile("st.shared.b32 [%0], %1;" ::"r"(a), "r"(v) : "memory"); }
__device__ __forceinline__ void sts2(uint32_t a, uint32_t v0, uint32_t v1) { asm volatile("st.shared.v2.b32 [%0], {%1,%2};" ::"r"(a), "r"(v0), "r"(v1) : "memory"); }
__device__ __forceinline__ void sts4(uint32_t a, uint32_t v0, uint32_t v1, uint32_t v2, uint32_t v3) { asm volatile("st.shared.v4.b32 [%0], {%1,%2,%3,%4};" ::"r"(a), "r"(v0), "r"(v1), "r"(v2), "r"(v3) : "memory"); }
__device__ __forceinline__ void bar_sync(int id, int n) { asm volatile("bar.sync %0, %1;" ::"r"(id), "r"(n) : "memory"); }
__device__ __forceinline__ void bar_arrive(int id, int n) { asm volatile("bar.arrive %0, %1;" ::"r"(id), "r"(n) : "memory"); }
__device__ __forceinline__ void red_add(unsigned* p, unsigned v) { asm volatile("red.relaxed.gpu.global.add.u32 [%0], %1;" ::"l"(p), "r"(v) : "memory"); }
__device__ __forceinline__ bool any(bool p) { return __any_sync(0xffffffffu, p); }
constexpr int SPIN_MAX = 1 << 20;
__device__ __forceinline__ void wait_cnt(const unsigned* p, unsigned target) {
  int it = 0;
  while (any((int)(ld_rlx(p) - target) < 0) && ++it < SPIN_MAX) {}
}
__device__ __forceinline__ uint32_t pack_bf16(float lo, float hi) { uint32_t r; asm("cvt.rn.bf16x2.f32 %0, %1, %2;" : "=r"(r) : "f"(hi), "f"(lo)); return r; }
__device__ __forceinline__ float bf_lo(uint32_t v) { return __uint_as_float(v << 16); }
__device__ __forceinline__ float bf_hi(uint32_t v) { return __uint_as_float(v & 0xffff0000u); }
__device__ __forceinline__ uint32_t hadd2(uint32_t a, uint32_t b) { uint32_t r; asm("add.rn.bf16x2 %0, %1, %2;" : "=r"(r) : "r"(a), "r"(b)); return r; }
__device__ __forceinline__ uint32_t hmul2(uint32_t a, uint32_t b) { uint32_t r; asm("mul.rn.bf16x2 %0, %1, %2;" : "=r"(r) : "r"(a), "r"(b)); return r; }
__device__ __forceinline__ uint32_t hfma2(uint32_t a, uint32_t b, uint32_t c) { uint32_t r; asm("fma.rn.bf16x2 %0, %1, %2, %3;" : "=r"(r) : "r"(a), "r"(b), "r"(c)); return r; }
__device__ __forceinline__ float rbf(float x) { uint32_t r; asm("cvt.rn.bf16x2.f32 %0, %1, %2;" : "=r"(r) : "f"(x), "f"(0.0f)); return __uint_as_float(r); }
__device__ __forceinline__ void stmatrix4(uint32_t a, uint32_t r0, uint32_t r1, uint32_t r2, uint32_t r3) {
  asm volatile("stmatrix.sync.aligned.m8n8.x4.shared.b16 [%0], {%1,%2,%3,%4};" ::"r"(a), "r"(r0), "r"(r1), "r"(r2), "r"(r3) : "memory");
}
__device__ __forceinline__ void stmatrix2(uint32_t a, uint32_t r0, uint32_t r1) {
  asm volatile("stmatrix.sync.aligned.m8n8.x2.shared.b16 [%0], {%1,%2};" ::"r"(a), "r"(r0), "r"(r1) : "memory");
}
__device__ __forceinline__ void stmatrix4t(uint32_t a, uint32_t r0, uint32_t r1, uint32_t r2, uint32_t r3) {
  asm volatile("stmatrix.sync.aligned.m8n8.x4.trans.shared.b16 [%0], {%1,%2,%3,%4};" ::"r"(a), "r"(r0), "r"(r1), "r"(r2), "r"(r3) : "memory");
}
__device__ __forceinline__ uint32_t movm(uint32_t a) { uint32_t r; asm("movmatrix.sync.aligned.m8n8.trans.b16 %0, %1;" : "=r"(r) : "r"(a)); return r; }
template <bool ACC> __device__ __forceinline__ void mma16(float* d, uint32_t a0, uint32_t a1, uint32_t a2, uint32_t a3, uint32_t b0, uint32_t b1) {
  if (ACC) asm("mma.sync.aligned.m16n8k16.row.col.f32.bf16.bf16.f32 {%0,%1,%2,%3}, {%4,%5,%6,%7}, {%8,%9}, {%0,%1,%2,%3};"
               : "+f"(d[0]), "+f"(d[1]), "+f"(d[2]), "+f"(d[3]) : "r"(a0), "r"(a1), "r"(a2), "r"(a3), "r"(b0), "r"(b1));
  else asm("mma.sync.aligned.m16n8k16.row.col.f32.bf16.bf16.f32 {%0,%1,%2,%3}, {%4,%5,%6,%7}, {%8,%9}, {%10,%10,%10,%10};"
           : "=f"(d[0]), "=f"(d[1]), "=f"(d[2]), "=f"(d[3]) : "r"(a0), "r"(a1), "r"(a2), "r"(a3), "r"(b0), "r"(b1), "f"(0.f));
}
__device__ __forceinline__ uint32_t pin(uint32_t v) { uint32_t r; asm volatile("shfl.sync.bfly.b32 %0, %1, 0, 31, 0xffffffff;" : "=r"(r) : "r"(v)); return r; }
template <class T> __device__ __forceinline__ T* pin(T* p) {
  const uint64_t a = reinterpret_cast<uint64_t>(p);
  return reinterpret_cast<T*>((uint64_t)pin((uint32_t)a) | ((uint64_t)pin((uint32_t)(a >> 32)) << 32));
}
__device__ __forceinline__ uint32_t upin(uint32_t v) { return __shfl_sync(0xffffffffu, v, 0); }
template <class T> __device__ __forceinline__ T* upin(T* p) {
  const uint64_t a = reinterpret_cast<uint64_t>(p);
  return reinterpret_cast<T*>((uint64_t)upin((uint32_t)a) | ((uint64_t)upin((uint32_t)(a >> 32)) << 32));
}
__device__ __forceinline__ bool elect() {
  uint32_t p;
  asm volatile("{\n.reg .pred P;\nelect.sync _|P, 0xffffffff;\nselp.u32 %0, 1, 0, P;\n}" : "=r"(p));
  return p;
}
__device__ __forceinline__ uint32_t set_tag(uint32_t w, uint32_t tag) { uint32_t r; asm("lop3.b32 %0, %1, 0xfffffffe, %2, 0xea;" : "=r"(r) : "r"(w), "r"(tag)); return r; }
__device__ __forceinline__ uint32_t diff2(uint32_t a, uint32_t b, uint32_t tag) { uint32_t r; asm("lop3.b32 %0, %1, %2, %3, 0x7e;" : "=r"(r) : "r"(a), "r"(b), "r"(tag)); return r; }
__device__ __forceinline__ float2 cmul(float2 a, float2 b) { return make_float2(a.x * b.x - a.y * b.y, a.x * b.y + a.y * b.x); }

template<int TB> __device__ __forceinline__ void wgmma_ss_160_0(float (&d)[80], uint32_t al, uint32_t ah, uint32_t bl, uint32_t bh) {
  asm volatile("{\n.reg .b64 da, db;\nmov.b64 da, {%80, %81};\nmov.b64 db, {%82, %83};\n"
    "wgmma.mma_async.sync.aligned.m64n160k16.f32.bf16.bf16 {%0,%1,%2,%3,%4,%5,%6,%7,%8,%9,%10,%11,%12,%13,%14,%15,%16,%17,%18,%19,%20,%21,%22,%23,%24,%25,%26,%27,%28,%29,%30,%31,%32,%33,%34,%35,%36,%37,%38,%39,%40,%41,%42,%43,%44,%45,%46,%47,%48,%49,%50,%51,%52,%53,%54,%55,%56,%57,%58,%59,%60,%61,%62,%63,%64,%65,%66,%67,%68,%69,%70,%71,%72,%73,%74,%75,%76,%77,%78,%79}, da, db, 1, 1, 1, 1, %84;\n}\n"
    : "+f"(d[0]),"+f"(d[1]),"+f"(d[2]),"+f"(d[3]),"+f"(d[4]),"+f"(d[5]),"+f"(d[6]),"+f"(d[7]),"+f"(d[8]),"+f"(d[9]),"+f"(d[10]),"+f"(d[11]),"+f"(d[12]),"+f"(d[13]),"+f"(d[14]),"+f"(d[15]),"+f"(d[16]),"+f"(d[17]),"+f"(d[18]),"+f"(d[19]),"+f"(d[20]),"+f"(d[21]),"+f"(d[22]),"+f"(d[23]),"+f"(d[24]),"+f"(d[25]),"+f"(d[26]),"+f"(d[27]),"+f"(d[28]),"+f"(d[29]),"+f"(d[30]),"+f"(d[31]),"+f"(d[32]),"+f"(d[33]),"+f"(d[34]),"+f"(d[35]),"+f"(d[36]),"+f"(d[37]),"+f"(d[38]),"+f"(d[39]),"+f"(d[40]),"+f"(d[41]),"+f"(d[42]),"+f"(d[43]),"+f"(d[44]),"+f"(d[45]),"+f"(d[46]),"+f"(d[47]),"+f"(d[48]),"+f"(d[49]),"+f"(d[50]),"+f"(d[51]),"+f"(d[52]),"+f"(d[53]),"+f"(d[54]),"+f"(d[55]),"+f"(d[56]),"+f"(d[57]),"+f"(d[58]),"+f"(d[59]),"+f"(d[60]),"+f"(d[61]),"+f"(d[62]),"+f"(d[63]),"+f"(d[64]),"+f"(d[65]),"+f"(d[66]),"+f"(d[67]),"+f"(d[68]),"+f"(d[69]),"+f"(d[70]),"+f"(d[71]),"+f"(d[72]),"+f"(d[73]),"+f"(d[74]),"+f"(d[75]),"+f"(d[76]),"+f"(d[77]),"+f"(d[78]),"+f"(d[79])
    : "r"(al), "r"(ah), "r"(bl), "r"(bh), "n"(TB));
}
template<int TB> __device__ __forceinline__ void wgmma_ss_144_0(float (&d)[80], uint32_t al, uint32_t ah, uint32_t bl, uint32_t bh) {
  asm volatile("{\n.reg .b64 da, db;\nmov.b64 da, {%72, %73};\nmov.b64 db, {%74, %75};\n"
    "wgmma.mma_async.sync.aligned.m64n144k16.f32.bf16.bf16 {%0,%1,%2,%3,%4,%5,%6,%7,%8,%9,%10,%11,%12,%13,%14,%15,%16,%17,%18,%19,%20,%21,%22,%23,%24,%25,%26,%27,%28,%29,%30,%31,%32,%33,%34,%35,%36,%37,%38,%39,%40,%41,%42,%43,%44,%45,%46,%47,%48,%49,%50,%51,%52,%53,%54,%55,%56,%57,%58,%59,%60,%61,%62,%63,%64,%65,%66,%67,%68,%69,%70,%71}, da, db, 1, 1, 1, 1, %76;\n}\n"
    : "+f"(d[0]),"+f"(d[1]),"+f"(d[2]),"+f"(d[3]),"+f"(d[4]),"+f"(d[5]),"+f"(d[6]),"+f"(d[7]),"+f"(d[8]),"+f"(d[9]),"+f"(d[10]),"+f"(d[11]),"+f"(d[12]),"+f"(d[13]),"+f"(d[14]),"+f"(d[15]),"+f"(d[16]),"+f"(d[17]),"+f"(d[18]),"+f"(d[19]),"+f"(d[20]),"+f"(d[21]),"+f"(d[22]),"+f"(d[23]),"+f"(d[24]),"+f"(d[25]),"+f"(d[26]),"+f"(d[27]),"+f"(d[28]),"+f"(d[29]),"+f"(d[30]),"+f"(d[31]),"+f"(d[32]),"+f"(d[33]),"+f"(d[34]),"+f"(d[35]),"+f"(d[36]),"+f"(d[37]),"+f"(d[38]),"+f"(d[39]),"+f"(d[40]),"+f"(d[41]),"+f"(d[42]),"+f"(d[43]),"+f"(d[44]),"+f"(d[45]),"+f"(d[46]),"+f"(d[47]),"+f"(d[48]),"+f"(d[49]),"+f"(d[50]),"+f"(d[51]),"+f"(d[52]),"+f"(d[53]),"+f"(d[54]),"+f"(d[55]),"+f"(d[56]),"+f"(d[57]),"+f"(d[58]),"+f"(d[59]),"+f"(d[60]),"+f"(d[61]),"+f"(d[62]),"+f"(d[63]),"+f"(d[64]),"+f"(d[65]),"+f"(d[66]),"+f"(d[67]),"+f"(d[68]),"+f"(d[69]),"+f"(d[70]),"+f"(d[71])
    : "r"(al), "r"(ah), "r"(bl), "r"(bh), "n"(TB));
}
template<int TB> __device__ __forceinline__ void wgmma_ss_96_0(float (&d)[80], uint32_t al, uint32_t ah, uint32_t bl, uint32_t bh) {
  asm volatile("{\n.reg .b64 da, db;\nmov.b64 da, {%48, %49};\nmov.b64 db, {%50, %51};\n"
    "wgmma.mma_async.sync.aligned.m64n96k16.f32.bf16.bf16 {%0,%1,%2,%3,%4,%5,%6,%7,%8,%9,%10,%11,%12,%13,%14,%15,%16,%17,%18,%19,%20,%21,%22,%23,%24,%25,%26,%27,%28,%29,%30,%31,%32,%33,%34,%35,%36,%37,%38,%39,%40,%41,%42,%43,%44,%45,%46,%47}, da, db, 1, 1, 1, 1, %52;\n}\n"
    : "+f"(d[0]),"+f"(d[1]),"+f"(d[2]),"+f"(d[3]),"+f"(d[4]),"+f"(d[5]),"+f"(d[6]),"+f"(d[7]),"+f"(d[8]),"+f"(d[9]),"+f"(d[10]),"+f"(d[11]),"+f"(d[12]),"+f"(d[13]),"+f"(d[14]),"+f"(d[15]),"+f"(d[16]),"+f"(d[17]),"+f"(d[18]),"+f"(d[19]),"+f"(d[20]),"+f"(d[21]),"+f"(d[22]),"+f"(d[23]),"+f"(d[24]),"+f"(d[25]),"+f"(d[26]),"+f"(d[27]),"+f"(d[28]),"+f"(d[29]),"+f"(d[30]),"+f"(d[31]),"+f"(d[32]),"+f"(d[33]),"+f"(d[34]),"+f"(d[35]),"+f"(d[36]),"+f"(d[37]),"+f"(d[38]),"+f"(d[39]),"+f"(d[40]),"+f"(d[41]),"+f"(d[42]),"+f"(d[43]),"+f"(d[44]),"+f"(d[45]),"+f"(d[46]),"+f"(d[47])
    : "r"(al), "r"(ah), "r"(bl), "r"(bh), "n"(TB));
}
template<int TB> __device__ __forceinline__ void wgmma_ss_48_48(float (&d)[80], uint32_t al, uint32_t ah, uint32_t bl, uint32_t bh) {
  asm volatile("{\n.reg .b64 da, db;\nmov.b64 da, {%24, %25};\nmov.b64 db, {%26, %27};\n"
    "wgmma.mma_async.sync.aligned.m64n48k16.f32.bf16.bf16 {%0,%1,%2,%3,%4,%5,%6,%7,%8,%9,%10,%11,%12,%13,%14,%15,%16,%17,%18,%19,%20,%21,%22,%23}, da, db, 1, 1, 1, 1, %28;\n}\n"
    : "+f"(d[48]),"+f"(d[49]),"+f"(d[50]),"+f"(d[51]),"+f"(d[52]),"+f"(d[53]),"+f"(d[54]),"+f"(d[55]),"+f"(d[56]),"+f"(d[57]),"+f"(d[58]),"+f"(d[59]),"+f"(d[60]),"+f"(d[61]),"+f"(d[62]),"+f"(d[63]),"+f"(d[64]),"+f"(d[65]),"+f"(d[66]),"+f"(d[67]),"+f"(d[68]),"+f"(d[69]),"+f"(d[70]),"+f"(d[71])
    : "r"(al), "r"(ah), "r"(bl), "r"(bh), "n"(TB));
}
__device__ __forceinline__ void wgmma_rs_72(float (&d)[36], uint32_t a0, uint32_t a1, uint32_t a2, uint32_t a3, uint32_t bl, uint32_t bh, int sd) {
  asm volatile("{\n.reg .pred p;\n.reg .b64 db;\nsetp.ne.b32 p, %42, 0;\nmov.b64 db, {%40, %41};\n"
    "wgmma.mma_async.sync.aligned.m64n72k16.f32.bf16.bf16 {%0,%1,%2,%3,%4,%5,%6,%7,%8,%9,%10,%11,%12,%13,%14,%15,%16,%17,%18,%19,%20,%21,%22,%23,%24,%25,%26,%27,%28,%29,%30,%31,%32,%33,%34,%35}, {%36,%37,%38,%39}, db, p, 1, 1, 1;\n}\n"
    : "+f"(d[0]),"+f"(d[1]),"+f"(d[2]),"+f"(d[3]),"+f"(d[4]),"+f"(d[5]),"+f"(d[6]),"+f"(d[7]),"+f"(d[8]),"+f"(d[9]),"+f"(d[10]),"+f"(d[11]),"+f"(d[12]),"+f"(d[13]),"+f"(d[14]),"+f"(d[15]),"+f"(d[16]),"+f"(d[17]),"+f"(d[18]),"+f"(d[19]),"+f"(d[20]),"+f"(d[21]),"+f"(d[22]),"+f"(d[23]),"+f"(d[24]),"+f"(d[25]),"+f"(d[26]),"+f"(d[27]),"+f"(d[28]),"+f"(d[29]),"+f"(d[30]),"+f"(d[31]),"+f"(d[32]),"+f"(d[33]),"+f"(d[34]),"+f"(d[35])
    : "r"(a0), "r"(a1), "r"(a2), "r"(a3), "r"(bl), "r"(bh), "r"(sd));
}
__device__ __forceinline__ void wgmma_rs_48(float (&d)[24], uint32_t a0, uint32_t a1, uint32_t a2, uint32_t a3, uint32_t bl, uint32_t bh, int sd) {
  asm volatile("{\n.reg .pred p;\n.reg .b64 db;\nsetp.ne.b32 p, %30, 0;\nmov.b64 db, {%28, %29};\n"
    "wgmma.mma_async.sync.aligned.m64n48k16.f32.bf16.bf16 {%0,%1,%2,%3,%4,%5,%6,%7,%8,%9,%10,%11,%12,%13,%14,%15,%16,%17,%18,%19,%20,%21,%22,%23}, {%24,%25,%26,%27}, db, p, 1, 1, 1;\n}\n"
    : "+f"(d[0]),"+f"(d[1]),"+f"(d[2]),"+f"(d[3]),"+f"(d[4]),"+f"(d[5]),"+f"(d[6]),"+f"(d[7]),"+f"(d[8]),"+f"(d[9]),"+f"(d[10]),"+f"(d[11]),"+f"(d[12]),"+f"(d[13]),"+f"(d[14]),"+f"(d[15]),"+f"(d[16]),"+f"(d[17]),"+f"(d[18]),"+f"(d[19]),"+f"(d[20]),"+f"(d[21]),"+f"(d[22]),"+f"(d[23])
    : "r"(a0), "r"(a1), "r"(a2), "r"(a3), "r"(bl), "r"(bh), "r"(sd));
}
template<int N,int OFF,int TB> __device__ __forceinline__ void wgmma_ss(float (&d)[80], uint32_t al, uint32_t ah, uint32_t bl, uint32_t bh) {
  if constexpr (N==160) wgmma_ss_160_0<TB>(d, al, ah, bl, bh);
  else if constexpr (N==144) wgmma_ss_144_0<TB>(d, al, ah, bl, bh);
  else if constexpr (N==96) wgmma_ss_96_0<TB>(d, al, ah, bl, bh);
  else if constexpr (N==48) wgmma_ss_48_48<TB>(d, al, ah, bl, bh);
}

__device__ __forceinline__ void dft3(float2& a, float2& b, float2& c) {
  const float s = 0.86602540378443864676f;
  float2 t = make_float2(b.x + c.x, b.y + c.y), d = make_float2(b.x - c.x, b.y - c.y);
  float2 m = make_float2(fmaf(-0.5f, t.x, a.x), fmaf(-0.5f, t.y, a.y));
  a = make_float2(a.x + t.x, a.y + t.y);
  b = make_float2(fmaf(s, d.y, m.x), fmaf(-s, d.x, m.y));
  c = make_float2(fmaf(-s, d.y, m.x), fmaf(s, d.x, m.y));
}
__device__ __forceinline__ void dft9(float2 (&x)[9]) {
  const float2 w1 = make_float2(0.76604444311897803520f, -0.64278760968653932632f);
  const float2 w2 = make_float2(0.17364817766693034885f, -0.98480775301220805937f);
  const float2 w4 = make_float2(-0.93969262078590838405f, -0.34202014332566873304f);
  dft3(x[0], x[3], x[6]); dft3(x[1], x[4], x[7]); dft3(x[2], x[5], x[8]);
  x[4] = cmul(x[4], w1); x[7] = cmul(x[7], w2); x[5] = cmul(x[5], w2); x[8] = cmul(x[8], w4);
  dft3(x[0], x[1], x[2]); dft3(x[3], x[4], x[5]); dft3(x[6], x[7], x[8]);
  float2 t;
  t = x[1]; x[1] = x[3]; x[3] = t;
  t = x[2]; x[2] = x[6]; x[6] = t;
  t = x[5]; x[5] = x[7]; x[7] = t;
}

__device__ __forceinline__ uint32_t* mod_ptr(Scratch* sc, int u, int t128) {
  const int i = t128 & 15;
  return u < 72 ? sc->moda + (t128 >> 4) * (2 * D_) + 16 * u + 2 * (i & 7) + (i >> 3) : sc->mod + 16 * (u - 72) + i;
}
__device__ __forceinline__ void mod_unit(Scratch* sc, int u, int t128, uint32_t sw_, uint32_t bar, int ph, uint32_t rb, uint32_t tag) {
  const int w = t128 >> 5, l = t128 & 31;
  uint32_t b[18];
#pragma unroll
  for (int i = 0; i < 18; i++) b[i] = lds(red + 512 + (72 * w + 4 * i + (l & 3)) * 4);
  const uint32_t sa = pin(sw_ + (144 * w + (l & 7) + 8 * (l >> 4)) * 32 + (((l >> 3) ^ (l >> 2)) & 1) * 16);
  const uint32_t sr = pin(rb + (l >> 2) * 16 + w * 4);
  uint32_t* const dst = pin(mod_ptr(sc, u, t128));
  const int kind = u / 36;
  const float mul = __uint_as_float(pin(__float_as_uint(kind == 0 ? 16.0f : 1.0f))), add = __uint_as_float(pin(__float_as_uint(kind == 1 || kind == 4 ? 1.0f : 0.0f)));
  mbar_wait(bar, ph);
  if (t128 == 0 && u < 72) TS(10);
  float d[3][4];
#pragma unroll
  for (int i = 0; i < 9; i++) {
    uint32_t a0, a1, a2, a3;
    asm volatile("ldmatrix.sync.aligned.m8n8.x4.trans.shared.b16 {%0,%1,%2,%3}, [%4];" : "=r"(a0), "=r"(a1), "=r"(a2), "=r"(a3) : "r"(sa + i * 512) : "memory");
    if (i < 3) mma16<false>(d[i], a0, a1, a2, a3, b[2 * i], b[2 * i + 1]);
    else mma16<true>(d[i % 3], a0, a1, a2, a3, b[2 * i], b[2 * i + 1]);
  }
  if ((l & 3) == 0) { sts(sr, __float_as_uint(d[0][0] + d[1][0] + d[2][0])); sts(sr + 128, __float_as_uint(d[0][2] + d[1][2] + d[2][2])); }
  bar_sync(4, 128);
  const uint4 v = lds4(rb + (l & 15) * 16);
  const float m = rbf(fmaf(rbf((__uint_as_float(v.x) + __uint_as_float(v.y)) + (__uint_as_float(v.z) + __uint_as_float(v.w))), mul, add));
  if (u < 72 || t128 < 16) *dst = __float_as_uint(m) | tag;
}

__device__ __forceinline__ void ln_stats2(const float (&a)[18], const float (&b)[18], float sc, float& oa, float& ra, float& ob, float& rb) {
  float v[4] = {0.f, 0.f, 0.f, 0.f}, w[4] = {0.f, 0.f, 0.f, 0.f};
#pragma unroll
  for (int i = 0; i < 18; i += 2) {
    v[0] += a[i]; v[1] = fmaf(a[i], a[i], v[1]); v[2] += b[i]; v[3] = fmaf(b[i], b[i], v[3]);
    w[0] += a[i + 1]; w[1] = fmaf(a[i + 1], a[i + 1], w[1]); w[2] += b[i + 1]; w[3] = fmaf(b[i + 1], b[i + 1], w[3]);
  }
#pragma unroll
  for (int e = 0; e < 4; e++) v[e] += w[e];
#pragma unroll
  for (int o = 16; o; o >>= 1) {
#pragma unroll
    for (int e = 0; e < 4; e++) v[e] += __shfl_xor_sync(0xffffffffu, v[e], o);
  }
  const float ma = v[0] * (1.0f / D_), mb = v[2] * (1.0f / D_);
  ra = sc * rsqrtf(fmaxf(fmaf(-ma, ma, v[1] * (1.0f / D_)), 0.f) + 1e-5f);
  rb = sc * rsqrtf(fmaxf(fmaf(-mb, mb, v[3] * (1.0f / D_)), 0.f) + 1e-5f);
  oa = -ma * ra; ob = -mb * rb;
}

__device__ __forceinline__ float tmat(int c, int q, int j) {
  const int ph = q == 1 ? 1024 * j : (q >> 1) * (c + 128 * j) + 512 * (q & 1);
  return __cosf((float)(((ph + 1024) & 2047) - 1024) * (6.283185307179586f / 2048.0f));
}
__device__ __forceinline__ uint32_t line_off(int k1, int kap, int pi, int f) {
  int kd = 64 * k1 + 9 * kap;
  if (kap == 0 && k1 > 4) kd -= 288;
  if (kd >= D_) kd -= D_;
  return pi * 2400 + ((min(kd, D_ - kd) ^ f) << 3);
}

constexpr int JSK = 5;
struct Ring { uint32_t st, ph; };
template <bool G2, class T> __device__ __forceinline__ void ring_next(T& st, T& ph) {
  if (++st == NST) st = 0;
  ph ^= ((G2 ? 0xDu : 0x1u) >> st) & 1;
}
__device__ __forceinline__ void arrive_if(uint32_t a, uint32_t p) {
  asm volatile("{\n.reg .pred p;\nsetp.ne.u32 p, %1, 0;\n@p mbarrier.arrive.shared::cta.b64 _, [%0];\n}" ::"r"(a), "r"(p) : "memory");
}
template <int NA> __device__ __forceinline__ void reg_fence_n(float (&d)[80]) {
#pragma unroll
  for (int i = 0; i < NA; i++) asm volatile("" : "+f"(d[i])::"memory");
}
template <int MODE>
__device__ __forceinline__ void gemm_main(float (&acc)[80], uint32_t da0, uint32_t da1, uint32_t db0, uint32_t db1, int wg, Ring& rg,
                                          uint32_t* x1p, const uint32_t (&xr)[18]) {
  static_assert(JSK == NST - 1, "the held slot is the first one that is not refilled by GEMM1");
  constexpr int NKB = MODE == 3 ? 36 : 32;
  constexpr uint32_t HA = 0x40000040u, HB = MODE == 3 ? 0x40000040u : 0x80000020u;
  constexpr uint32_t KA = 2048 >> 4, KB = MODE == 3 ? (32 >> 4) : (1024 >> 4);
  constexpr int NA = MODE ? 72 : 80;
  const uint32_t t = threadIdx.x & 127;
  const uint32_t eb = full0 + 8 * NST;
  uint32_t pb = 0, rel = t == 0, prel = 0, ok = 0;
  int n = MODE == 3 ? NKB - JSK : X1K + 2 * wg;
#pragma unroll 1
  for (int pass = MODE == 3 ? 0 : -1;; pass++) {
#pragma unroll 1
    do {
      const uint32_t so = rg.st * (STAGE >> 4), cb = eb + 8 * rg.st;
      if (__builtin_expect(!ok, 0)) mbar_wait(full0 + 8 * rg.st, rg.ph);
      reg_fence_n<NA>(acc);
      wg_fence();
#pragma unroll
      for (int k = 0; k < 4; k++) {
        if (k == 3) { ring_next<MODE == 3>(rg.st, rg.ph); ok = PEEK ? mbar_test(full0 + 8 * rg.st, rg.ph) : 0; }
        if (MODE == 0) wgmma_ss<160, 0, 1>(acc, da0 + so + k * KA, HA, db0 + so + k * KB, HB);
        else if (MODE == 3) wgmma_ss<144, 0, 0>(acc, da0 + so + k * KA, HA, db0 + so + k * KB, HB);
        else {
          wgmma_ss<96, 0, 1>(acc, da0 + so + k * KA, HA, db0 + so + k * KB, HB);
          wgmma_ss<48, 48, 1>(acc, da1 + so + k * KA, HA, db1 + so + k * KB, HB);
        }
      }
      wg_commit();
      wg_wait<1>();
      reg_fence_n<NA>(acc);
      arrive_if(pb, prel);
      pb = cb; prel = rel;
    } while (--n);
    if (pass == 2 - wg) break;
    if (MODE != 3 && pass < 0) {
      if (blockIdx.x < 128) {
#pragma unroll
        for (int i = 0; i < 9; i++) { x1p[32 * i] = xr[i]; x1p[128 * 288 + 32 * i] = xr[9 + i]; }
      }
      n = NKB - JSK - X1K - 2 * wg;
      continue;
    }
    n = 1;
    if (pass == 0) {
      if (MODE != 3) prel = rel & wg;
      else rel = 0;
      n = JSK - 1 + wg;
      if (!wg) continue;
      wg_wait<0>();
      arrive_if(pb, prel);
      prel = 0;
    }
    bar_sync(1, 256);
  }
  wg_wait<0>();
  reg_fence_n<NA>(acc);
  if (MODE != 3) arrive_if(pb, prel & ~wg);
}

__device__ __forceinline__ float gelu_arg(float h) { return h * fmaf(8.0f * 0.044715f * 0.7978845608028654f, h * h, 2.0f * 0.7978845608028654f); }

__device__ __forceinline__ int kb2_order(int i) { const int wv = i / 6; return 6 * (i - 6 * wv) + ((0x431250 >> (4 * wv)) & 7); }

__device__ __forceinline__ void wait_flags(const unsigned* base, int n, int idx, unsigned target, uint64_t& ready) {
  if ((ready >> idx) & 1) return;
  const int l = threadIdx.x & 31;
  int it = 0;
  while (true) {
    unsigned a = ld_rlx(base + l), b = l + 32 < n ? ld_rlx(base + l + 32) : target;
    ready = (uint64_t)__ballot_sync(0xffffffffu, (int)(a - target) >= 0) | ((uint64_t)__ballot_sync(0xffffffffu, (int)(b - target) >= 0) << 32);
    if (((ready >> idx) & 1) || ++it > SPIN_MAX) break;
  }
  fence_async_glb();
}

enum { B_FULL = 0, B_EMPTY = 6, B_FLT = 12, B_Z1, B_Z2, B_GO, B_S4, B_S5, B_WM, B_NUM, B_W0 = B_NUM };

__global__ void __launch_bounds__(NTHR, 1)
fused_kernel(const Params p, const __grid_constant__ Maps maps) {
  extern __shared__ __align__(1024) uint8_t smem_raw[];
  const int tid = threadIdx.x, cta = blockIdx.x, t128 = tid & 127;
  const int wp = __shfl_sync(0xffffffffu, tid >> 5, 0), wg = wp >> 2;
  const int l = tid & 31, g = l >> 2, t = l & 3;
  Scratch* const sc = p.s;
  const bool rows = cta < 128;
  const int R = cta - 12;

  uint32_t xr[18];
  uint32_t cv[3];
  const unsigned ep = ld_rlx(&sc->cnt[C_EP]) + 1;
  if (tid == 0) TS(0);
  if (wg == 2) {
#pragma unroll
    for (int i = 0; i < 3; i++) cv[i] = ld_nc(reinterpret_cast<const uint32_t*>(p.c) + min(t128 + 128 * i, 287));
    if (wp == 9 && l < 9 && rows) {
      const int h = 9 * cta + l;
      prefetch_l2(reinterpret_cast<const uint8_t*>(p.wmod) + (size_t)(h >> 1) * (12 * D_) + (h & 1) * (2 * D_), 2 * D_);
    }
    if (tid == 256 && cta < 72) {
      mbar_init(full0 + 8 * B_W0, 1);
      fence_async_smem();
      mbar_expect(full0 + 8 * B_W0, 18432);
#pragma unroll 1
      for (int i = 0; i < 3; i++) tma2d(sbase + O_P2 + i * 6144, &maps.wm, 16 * cta, 192 * i, full0 + 8 * B_W0);
    }
    __syncwarp();
#pragma unroll 1
    for (int u = cta < 72 ? cta : 72 + cta; u < 216; u += u < 72 ? 72 : NCTA) if (u < 72 || t128 < 16) *mod_ptr(sc, u, t128) = 0;
    if (wp == 11 && smem_u32(smem_raw) != sbase) __trap();
    if (tid == 352) {
#pragma unroll 1
      for (int i = 0; i < B_NUM; i++) mbar_init(full0 + 8 * i, i == B_FLT ? 4 : i == B_WM ? 3 : (i >= B_EMPTY && i < B_FLT) || i == B_S4 || i == B_S5 ? 2 : 1);
      fence_async_smem();
    }
    if (wp == 10 && l < 13) asm volatile("prefetch.tensormap [%0];" ::"l"(&maps.w1a + l) : "memory");
    __syncwarp();
  }
  CK(0);
  auto load_x = [&]() {
    const uint32_t* xs = reinterpret_cast<const uint32_t*>(p.x) + (size_t)(cta + 256 * wp) * 288 + l;
#pragma unroll
    for (int i = 0; i < 9; i++) { xr[i] = ld_nc(xs + 32 * i); xr[9 + i] = ld_nc(xs + 128 * 288 + 32 * i); }
  };
  if (rows && wg < 2) load_x();
  if (tid == 64 && cta == NCTA - 1) prefetch_l2(p.tab, sizeof(T_TAB));
  __syncwarp();
  const uint32_t tag16 = (ep & 0x7fffu) | 0x8000u, tag1 = ep & 1u;

  if (wg == 2) {
#pragma unroll
    for (int i = 0; i < 3; i++) {
      const float c0 = bf_lo(cv[i]), c1 = bf_hi(cv[i]);
      sts(red + 512 + min(t128 + 128 * i, 287) * 4, pack_bf16(__fdividef(c0, 1.0f + __expf(-c0)), __fdividef(c1, 1.0f + __expf(-c1))));
    }
    bar_sync(4, 128);
    if (cta < 72) {
      mod_unit(sc, cta, t128, sbase + O_P2, full0 + 8 * B_W0, 0, red, tag16);
      if (t128 == 0) TS(25);
      if (MODBAR) bar_arrive(15, NTHR);
    }
    CK(1);
  }
  const int pi = R / 15, col0 = 20 * (R - 15 * pi);
  const int xu = DF_ * pi + col0, xv = DF_ * (pi ? 16 - pi : 8) + col0;
  auto load_filter = [&](int a) {
    const int x = (a & 1) ? xv : xu;
    const bool wide = (x & 15) > 12;
    mbar_expect(full0 + 8 * B_FLT, wide ? 12288 : 8192);
    tma2d(sbase + O_RAW + a * 12288, &maps.wf[a & 2], x & ~15, 0, full0 + 8 * B_FLT);
    if (wide) tma2d(sbase + O_RAW + a * 12288 + 8192, &maps.wf[(a & 2) + 1], (x & ~15) + 32, 0, full0 + 8 * B_FLT);
  };
  const int kap = 8 * ((wp & 3) ^ (wg & 1)) + g;
  uint4 af[4];
  if (rows) {
    uint32_t tb[4];
#pragma unroll
    for (int i = 0; i < 4; i++) tb[i] = pack_bf16(tmat(cta, 8 * (i >> 1) + g, 2 * t + 8 * (i & 1)), tmat(cta, 8 * (i >> 1) + g, 2 * t + 8 * (i & 1) + 1));
    uint32_t sb1[3], lo[9];
#pragma unroll
    for (int i = 0; i < 4; i++) tb[i] = pin(tb[i]);
#pragma unroll
    for (int i = 0; i < 3; i++) {
      const int d = 48 * wp + 16 * i + (l & 15);
      sb1[i] = pin(sbase + O_B1 + (l >> 4) * 9216 + (d % 9) * 1024 + (d & 63) * 16);
    }
    const uint32_t snt = pin(sbase + O_NRM + ((l & 7) + 8 * (l >> 4)) * 1168 + (48 * wp + (l & 8)) * 2);
    if (wg < 2) {
#pragma unroll
      for (int k1 = 0; k1 < 9; k1++) lo[k1] = pin(sbase + O_Z1 + line_off(k1, kap, 4 * wg + t, cta & 3));
#pragma unroll
      for (int kk = 0; kk < 4; kk++) af[kk] = __ldg(p.tab + TB_F + kk * 128 + (t128 ^ (wg << 5)));
      float a[18], b[18];
#pragma unroll
      for (int i = 0; i < 9; i++) { a[2 * i] = bf_lo(xr[i]); a[2 * i + 1] = bf_hi(xr[i]); b[2 * i] = bf_lo(xr[9 + i]); b[2 * i + 1] = bf_hi(xr[9 + i]); }
      float oa, ra, ob, rb;
      ln_stats2(a, b, 1.0f, oa, ra, ob, rb);
      CK(1);
      const uint32_t sn = sbase + O_NRM + wp * 2336 + l * 4;
#pragma unroll
      for (int i = 0; i < 9; i++) {
        sts(sn + i * 128, pack_bf16(fmaf(a[2 * i], ra, oa), fmaf(a[2 * i + 1], ra, oa)));
        sts(sn + 1168 + i * 128, pack_bf16(fmaf(b[2 * i], rb, ob), fmaf(b[2 * i + 1], rb, ob)));
      }
      CK(2);
      bar_arrive(10, NTHR);
      bar_sync(1, 256);
      if (tid == 0) TS(2);
    } else {
      bar_sync(10, NTHR);
      CK(2);
    }
    float rs[3][8];
#pragma unroll
    for (int i = 0; i < 3; i++) {
      uint32_t a0, a1, a2, a3;
      asm volatile("ldmatrix.sync.aligned.m8n8.x4.trans.shared.b16 {%0,%1,%2,%3}, [%4];" : "=r"(a0), "=r"(a1), "=r"(a2), "=r"(a3)
                   : "r"(snt + 32 * i) : "memory");
      mma16<false>(&rs[i][0], a0, a1, a2, a3, tb[0], tb[1]);
      mma16<false>(&rs[i][4], a0, a1, a2, a3, tb[2], tb[3]);
    }
    CK(3);
    {
      uint2 ms[3], mc[3];
      const uint32_t* mp = pin(sc->moda + (cta >> 4) * (2 * D_) + 48 * wp + 2 * g);
      if (MODBAR && wg < 2 && cta < 72) bar_sync(15, NTHR);
      int it = 0;
#pragma unroll 1
      while (true) {
        uint32_t bad = 0;
#pragma unroll
        for (int i = 0; i < 3; i++) { ms[i] = ld_rlx2(mp + 16 * i); mc[i] = ld_rlx2(mp + D_ + 16 * i); }
#pragma unroll
        for (int i = 0; i < 3; i++) {
          ms[i].x ^= tag16; ms[i].y ^= tag16; mc[i].x ^= tag16; mc[i].y ^= tag16;
          bad |= ms[i].x | ms[i].y | mc[i].x | mc[i].y;
        }
        if (!any(bad & 0xffffu) || ++it > SPIN_MAX) break;
      }
      CK(4);
      if (tid == 0) TS(3);
#pragma unroll
      for (int i = 0; i < 3; i++) {
        const float c0 = __uint_as_float(mc[i].x), c1 = __uint_as_float(mc[i].y);
        const float s0 = t ? 0.f : __uint_as_float(ms[i].x), s1 = t ? 0.f : __uint_as_float(ms[i].y);
        stmatrix4(sb1[i], pack_bf16(fmaf(rs[i][0], c0, s0), rs[i][1] * c0), pack_bf16(fmaf(rs[i][2], c1, s1), rs[i][3] * c1),
                  pack_bf16(rs[i][4] * c0, rs[i][5] * c0), pack_bf16(rs[i][6] * c1, rs[i][7] * c1));
      }
    }
    fence_async_smem();
    CK(5);
    if (wg == 2) {
      bar_arrive(5, NTHR);
      if (R >= 0 && elect()) load_filter(wp - 8);
      __syncwarp();
    } else {
      bar_sync(5, NTHR);
      CK(6);
      float acc[36];
      const uint32_t db = (((sbase + O_B1 + wg * 9216) & 0x3FFFF) >> 4) | ((128 >> 4) << 16);
      wg_fence();
#pragma unroll
      for (int kk = 0; kk < 4; kk++) wgmma_rs_72(acc, af[kk].x, af[kk].y, af[kk].z, af[kk].w, db + kk * 16, 1024 >> 4, kk);
      wg_commit();
      wg_wait<0>();
      reg_fence(acc);
      CK(7);
      float2 za[9], zb[9];
#pragma unroll
      for (int i = 0; i < 9; i++) { za[i] = make_float2(acc[4 * i], acc[4 * i + 2]); zb[i] = make_float2(acc[4 * i + 1], acc[4 * i + 3]); }
      dft9(za); dft9(zb);
      if (kap == 0) {
#pragma unroll
        for (int k = 1; k < 5; k++) {
          float2 a = za[k], b = za[9 - k];
          za[k] = make_float2(a.x + b.x, a.y - b.y); za[9 - k] = make_float2(a.y + b.y, b.x - a.x);
          a = zb[k]; b = zb[9 - k];
          zb[k] = make_float2(a.x + b.x, a.y - b.y); zb[9 - k] = make_float2(a.y + b.y, b.x - a.x);
        }
        sts2(lo[0] + 288 * 8, set_tag(pack_bf16(za[0].y, 0.f), tag1), pack_bf16(zb[0].y, 0.f));
        za[0].y = 0.f; zb[0].y = 0.f;
      }
      __syncwarp();
#pragma unroll
      for (int k1 = 0; k1 < 9; k1++) sts2(lo[k1], set_tag(pack_bf16(za[k1].x, za[k1].y), tag1), pack_bf16(zb[k1].x, zb[k1].y));
      fence_async_smem();
      CK(8);
      bar_arrive(2 + wg, 160);
    }
  } else {
    __syncthreads();
  }

  if ((wp >> 1) == 4) {
    if (rows) {
      const int slot = 4 * (cta & 7) + ((cta >> 4) & 3) + 32 * (2 * (cta >> 6) + ((cta >> 3) & 1));
      const uint32_t c0 = upin(40 * slot), c1 = upin(60 * (wp - 8)), src = upin(sbase + O_Z1 + (wp - 8) * 9600);
      const CUtensorMap* mp = upin(&maps.z1);
      unsigned* hint = pin(&sc->cnt[C_Z1 + 32 * (wp - 8)]);
      bar_sync(wp - 6, 160);
      if (elect()) {
        tma_st2d(mp, src, c0, c1);
        HW();
        red_add(hint, 1);
        if (wp == 8) TS(4);
      }
    } else {
      int it = 0;
      while (any((ld_rlx(sc->moda + 36 * l) ^ tag16) & 0xffffu) && ++it < SPIN_MAX) {}
      if (elect()) { load_filter(wp - 8); load_filter(wp - 6); }
    }
    __syncwarp();
  }
  auto load_wm = [&](int u) {
    if (wp > 8 && elect()) {
      mbar_expect(full0 + 8 * B_WM, 6144);
      tma2d(sbase + O_NRM + (wp - 9) * 6144, &maps.wm, 16 * u, 192 * (wp - 9), full0 + 8 * B_WM);
    }
    __syncwarp();
  };
  if (R >= 0) {
    const int ln0 = wg < 2 ? 2 * wp : 8 + wp;
    const int nl = min(wg < 2 ? 2 : 1, DF_ - col0 - ln0);
    uint4 cf[2][4], G[4];
#pragma unroll
    for (int i = 0; i < 4; i++) {
      cf[0][i] = __ldg(p.tab + TB_P2 + i * 32 + l);
      cf[1][i] = __ldg(p.tab + TB_P2 + (pi ? i : 4 + i) * 32 + l);
      G[i] = __ldg(p.tab + TB_P2 + (8 + i) * 32 + l);
    }
    const uint32_t* zin = sc->z1 + (size_t)R * 5120;
    if (wp == 10) {
      const uint32_t* zu = upin(zin);
      if (elect()) mbar_expect(full0 + 8 * B_Z1, 20480);
      wait_cnt(&sc->cnt[C_Z1 + 32 * (pi >> 2)], 128 * ep);
      if (elect()) {
        bulk_ld(sbase + O_P2, zu, 20480, full0 + 8 * B_Z1);
        TS(12);
      }
      __syncwarp();
    }
    mbar_wait(full0 + 8 * B_FLT, 0);
    CK(9);
    float wn[16], wc[16];
#pragma unroll 1
    for (int ln = nl - 1; ln >= 0; ln--) {
      const int col = col0 + ln0 + ln, k2 = (57 * col) & 63;
      const bool cj = k2 > 32 || (k2 == 32 && col != 288);
      const float nr = ((col & 31) == 0 && col != 0 && col != 288 ? 0.5f : 1.0f) / ((float)S_ * D_), ni = cj ? -nr : nr;
#pragma unroll
      for (int i = 0; i < 16; i++) wn[i] = wc[i];
#pragma unroll
      for (int cl = 0; cl < 2; cl++) {
        const int v = cl ^ (cj && pi), e = ((v ? xv : xu) & 15) + ln0 + ln, sh = e < 32 ? 6 : 5;
        const uint32_t base = sbase + O_RAW + v * 12288 + (e < 32 ? 2 * e : 8192 - 64 + 2 * e), msk = e < 32 ? 0x30 : 0x10;
        const int dm = v ? (cj || pi ? -1 : 0) : 0;
#pragma unroll
        for (int tt = 0; tt < 4; tt++) {
          const int kc = g + 64 * (tt >> 1) + 16 * t + 8 * (tt & 1);
          uint32_t a = base + ((((cj ? -kc : kc) + dm) & 127) << sh);
          a ^= (a >> 3) & msk;
          wc[4 * tt + 2 * cl] = lds_bf(a) * nr; wc[4 * tt + 2 * cl + 1] = lds_bf(a + 24576) * ni;
        }
      }
    }
    const float al = pi ? 1.0f : 0.0f;
    CK(10);
    uint32_t off = pin(l * 160 + ((ln0 ^ (g & 3)) << 3));
    const CUtensorMap* mz2 = upin(&maps.z2);
    const uint32_t cz2 = upin(40 * R);
    unsigned* hz2 = pin(&sc->cnt[C_Z2]);
    mbar_wait(full0 + 8 * B_Z1, 0);
    CK(11);
    if (tid == 0) TS(8);
    if (wg == 2) load_wm(72 + cta);
#pragma unroll 1
    for (int ln = 0; ln < nl; ln++, off ^= 8) {
      uint2 v[4];
#pragma unroll
      for (int i = 0; i < 4; i++) v[i] = lds2(sbase + O_P2 + off + i * 5120);
      if (__builtin_expect(any((diff2(v[0].x, v[1].x, tag1) | diff2(v[2].x, v[3].x, tag1)) & 1), 0)) {
        FAILCNT(0);
        int it = 0;
        do {
#pragma unroll
          for (int i = 0; i < 4; i++) v[i] = ld_rlx2(reinterpret_cast<const uint8_t*>(zin) + off + i * 5120);
        } while (any((diff2(v[0].x, v[1].x, tag1) | diff2(v[2].x, v[3].x, tag1)) & 1) && ++it < SPIN_MAX);
      }
      float d[4][4];
      uint32_t A[8];
#pragma unroll
      for (int h = 0; h < 2; h++) {
        mma16<false>(d[2 * h], cf[0][0].x, cf[0][0].y, cf[0][0].z, cf[0][0].w, v[h].x, v[2 + h].x);
        mma16<false>(d[2 * h + 1], cf[1][0].x, cf[1][0].y, cf[1][0].z, cf[1][0].w, v[h].y, v[2 + h].y);
      }
#pragma unroll
      for (int h = 0; h < 2; h++)
#pragma unroll
        for (int L = 0; L < 2; L++) {
          const uint4 tw = cf[L][2 + h];
          const float* z = d[2 * h + L];
          const float2 z0 = cmul(make_float2(z[0], z[2]), make_float2(__uint_as_float(tw.x), __uint_as_float(tw.y)));
          const float2 z1 = cmul(make_float2(z[1], z[3]), make_float2(__uint_as_float(tw.z), __uint_as_float(tw.w)));
          A[4 * h + L] = pack_bf16(z0.x, z0.y); A[4 * h + 2 + L] = pack_bf16(z1.x, z1.y);
        }
#pragma unroll
      for (int tt = 0; tt < 4; tt++) {
        mma16<false>(d[tt], A[0], A[1], A[2], A[3], G[tt].x, G[tt].y);
        mma16<true>(d[tt], A[4], A[5], A[6], A[7], G[tt].z, G[tt].w);
      }
#pragma unroll
      for (int tt = 0; tt < 4; tt++) {
        const float ar = d[tt][0], aj = d[tt][1], br = d[tt][2], bj = d[tt][3];
        const float2 y1 = cmul(make_float2(fmaf(-al, bj, ar), fmaf(al, br, aj)), make_float2(wc[4 * tt], wc[4 * tt + 1]));
        const float2 y2 = cmul(make_float2(fmaf(al, ar, bj), fmaf(al, aj, -br)), make_float2(wc[4 * tt + 2], wc[4 * tt + 3]));
        A[2 * tt] = pack_bf16(fmaf(al, y2.x, y1.x), fmaf(-al, y2.y, -y1.y));
        A[2 * tt + 1] = pack_bf16(fmaf(al, y1.y, -y2.y), fmaf(al, y1.x, -y2.x));
      }
#pragma unroll
      for (int i = 0; i < 16; i++) wc[i] = wn[i];
#pragma unroll
      for (int tt = 0; tt < 4; tt++) {
        mma16<false>(d[tt], A[0], A[1], A[2], A[3], G[tt].x, G[tt].y);
        mma16<true>(d[tt], A[4], A[5], A[6], A[7], G[tt].z, G[tt].w);
      }
#pragma unroll
      for (int h = 0; h < 2; h++)
#pragma unroll
        for (int L = 0; L < 2; L++) {
          const uint4 tw = cf[L][2 + h];
          const float2 z0 = cmul(make_float2(d[2 * h][2 * L], d[2 * h][2 * L + 1]), make_float2(__uint_as_float(tw.x), __uint_as_float(tw.y)));
          const float2 z1 = cmul(make_float2(d[2 * h + 1][2 * L], d[2 * h + 1][2 * L + 1]), make_float2(__uint_as_float(tw.z), __uint_as_float(tw.w)));
          A[4 * h + 2 * L] = movm(pack_bf16(z0.x, z1.x)); A[4 * h + 2 * L + 1] = movm(pack_bf16(z0.y, z1.y));
        }
#pragma unroll
      for (int h = 0; h < 2; h++) {
        mma16<false>(d[0], cf[0][1].x, cf[0][1].y, cf[0][1].z, cf[0][1].w, A[4 * h], A[4 * h + 1]);
        mma16<false>(d[1], cf[1][1].x, cf[1][1].y, cf[1][1].z, cf[1][1].w, A[4 * h + 2], A[4 * h + 3]);
#pragma unroll
        for (int e = 0; e < 2; e++)
          sts2(sbase + O_P2 + off + (2 * h + e) * 5120, set_tag(pack_bf16(d[0][e], d[0][2 + e]), tag1), pack_bf16(d[1][e], d[1][2 + e]));
      }
      CK(12 + ln);
    }
    fence_async_smem();
    if (wp) bar_arrive(6, NTHR);
    else {
      bar_sync(6, NTHR);
      if (elect()) {
        tma_st2d(mz2, sbase + O_P2, cz2, 0);
        HW();
        red_add(hz2, 1);
        TS(9);
      }
      __syncwarp();
    }
  }
  if (wg == 2) {
#pragma unroll 1
    for (int u = 72 + cta, k = 0; u < 216; u += NCTA, k ^= 1) {
      if (R < 0) { fence_async_smem(); bar_sync(4, 128); load_wm(u); }
      mod_unit(sc, u, t128, sbase + O_NRM, full0 + 8 * B_WM, k, red + 256 - 256 * k, tag16);
    }
    fence_async_smem();
    CK(13);
  }

  const int grp = cta / 11, m1 = cta - 11 * grp;
  const bool helper = (m1 & 3) == 3;
  const int f1 = 384 * grp + (helper ? 192 : 128) * (m1 >> 2);
  const int d1 = 160 * (m1 & 3), flip = m1 >= 7;
  const int a1bytes = helper ? 24576 : 16384;
  auto load_a1 = [&](int st, int kb) {
    mbar_expect(full0 + 8 * st, STAGE);
    tma4d_ef(sbase + st * STAGE, helper ? &maps.w1b : &maps.w1a, 4 * (kb >> 3), 16 * (kb & 7), f1 >> 6, full0 + 8 * st);
  };

  if (rows) {
#pragma unroll
    for (int kk = 0; kk < 4; kk++) af[kk] = __ldg(p.tab + TB_E + kk * 128 + t128);
    uint32_t tb[4], sy[6];
#pragma unroll
    for (int i = 0; i < 4; i++) tb[i] = pack_bf16(tmat(cta, 2 * t + 8 * (i & 1), 8 * (i >> 1) + g), tmat(cta, 2 * t + 8 * (i & 1) + 1, 8 * (i >> 1) + g));
#pragma unroll
    for (int i = 0; i < 6; i++) {
      const int rr = 16 * (wp & 3) + g + 8 * (i & 1);
      sy[i] = pin(sbase + O_Y + (t * 584 + 64 * ((3 * wg + (i >> 1) + 63 - rr) % 9) + rr) * 4);
    }
#pragma unroll
    for (int i = 0; i < 4; i++) tb[i] = pin(tb[i]);
    const int slot = 4 * (cta >> 4) + ((cta >> 1) & 3) + 32 * (2 * ((cta >> 3) & 1) + (cta & 1));
    const uint32_t* zin = sc->z2 + (size_t)slot * 4800;
    if (wg == 2) {
      {
        uint4 v[4];
        const int i3 = min(t128 + 384, 431);
        int it = 0;
        while (true) {
          uint32_t bad = 0;
#pragma unroll
          for (int k = 0; k < 4; k++) v[k] = ld_rlx4(sc->mod + 4 * (k < 3 ? t128 + 128 * k : i3));
#pragma unroll
          for (int k = 0; k < 4; k++) {
            v[k].x ^= tag16; v[k].y ^= tag16; v[k].z ^= tag16; v[k].w ^= tag16;
            bad |= v[k].x | v[k].y | v[k].z | v[k].w;
          }
          if (!any(bad & 0xffffu) || ++it > SPIN_MAX) break;
        }
#pragma unroll
        for (int k = 0; k < 4; k++) sts4(sbase + O_MOD + 16 * (k < 3 ? t128 + 128 * k : i3), v[k].x, v[k].y, v[k].z, v[k].w);
      }
      CK(14);
      mbar_wait(full0 + 8 * B_Z2, 0);
      if (elect()) {
        load_a1(wp - 8, wp - 8);
        if (wp > 8 && wp - 8 < NG1) prefetch_l2(reinterpret_cast<const uint8_t*>(p.w1) + (size_t)(128 * (4 * ((wp - 8) >> 1) + (cta >> 5)) + 64 * (wp & 1) + 2 * (cta & 31)) * (2 * F_), 4 * F_);
      }
      __syncwarp();
    } else {
      uint32_t lo[9];
#pragma unroll
      for (int k1 = 0; k1 < 9; k1++) lo[k1] = pin(sbase + O_IN + line_off(k1, kap, 4 * wg + t, (cta >> 4) & 3));
      const uint32_t lx = pin(lo[0] + (kap ? 0 : 288 * 8));
      const uint32_t sb3 = pin(sbase + O_B3 + wg * 1024 + (l >> 4) * 2048 + (2 * (kap & 24) + (l & 15)) * 16);
      CK(14);
      if (wp == 0) {
        const uint32_t* zu = upin(zin);
        if (elect()) mbar_expect(full0 + 8 * B_Z2, 19200);
        wait_cnt(&sc->cnt[C_Z2], 120 * ep);
        if (elect()) {
          bulk_ld(sbase + O_IN, zu, 19200, full0 + 8 * B_Z2);
          TS(14);
        }
        __syncwarp();
      }
      mbar_wait(full0 + 8 * B_Z2, 0);
      CK(15);
      if (tid == 0) TS(11);
      uint2 v[10];
      uint32_t bad = 0;
#pragma unroll
      for (int k1 = 0; k1 < 10; k1++) v[k1] = lds2(k1 < 9 ? lo[k1] : lx);
#pragma unroll
      for (int k1 = 0; k1 < 10; k1 += 2) bad |= diff2(v[k1].x, v[k1 + 1].x, tag1);
      if (__builtin_expect(any(bad & 1), 0)) {
        FAILCNT(1);
        int it = 0;
        do {
          bad = 0;
#pragma unroll
          for (int k1 = 0; k1 < 10; k1++) v[k1] = ld_rlx2(reinterpret_cast<const uint8_t*>(zin) + ((k1 < 9 ? lo[k1] : lx) - (sbase + O_IN)));
#pragma unroll
          for (int k1 = 0; k1 < 10; k1 += 2) bad |= diff2(v[k1].x, v[k1 + 1].x, tag1);
        } while (any(bad & 1) && ++it < SPIN_MAX);
      }
      float2 za[9], zb[9];
#pragma unroll
      for (int i = 0; i < 9; i++) { za[i] = make_float2(bf_lo(v[i].x), bf_hi(v[i].x)); zb[i] = make_float2(bf_lo(v[i].y), bf_hi(v[i].y)); }
      if (kap == 0) {
#pragma unroll
        for (int k = 1; k < 5; k++) {
          float2 a = za[k], b = za[9 - k];
          za[k] = make_float2(a.x - b.y, a.y + b.x); za[9 - k] = make_float2(a.x + b.y, b.x - a.y);
          a = zb[k]; b = zb[9 - k];
          zb[k] = make_float2(a.x - b.y, a.y + b.x); zb[9 - k] = make_float2(a.x + b.y, b.x - a.y);
        }
        za[0].y = bf_lo(v[9].x); zb[0].y = bf_lo(v[9].y);
      }
      __syncwarp();
      dft9(za); dft9(zb);
#pragma unroll
      for (int n = 0; n < 8; n += 2) {
        const int i0 = (9 - n) % 9, i1 = 8 - n;
        stmatrix4(sb3 + n * 2048, pack_bf16(za[i0].x, zb[i0].x), pack_bf16(za[i0].y, zb[i0].y), pack_bf16(za[i1].x, zb[i1].x), pack_bf16(za[i1].y, zb[i1].y));
      }
      stmatrix2(sb3 + 8 * 2048, pack_bf16(za[1].x, zb[1].x), pack_bf16(za[1].y, zb[1].y));
      fence_async_smem();
    }
    CK(16);
    __syncthreads();
    CK(17);
    float acc[24];
    const uint32_t db = (((sbase + O_B3 + wg * 6144) & 0x3FFFF) >> 4) | ((128 >> 4) << 16);
    wg_fence();
#pragma unroll
    for (int kk = 0; kk < 4; kk++) wgmma_rs_48(acc, af[kk].x, af[kk].y, af[kk].z, af[kk].w, db + kk * 16, 1024 >> 4, kk);
    wg_commit();
    uint32_t ga[9];
    uint2 sh[9], sw[9];
    if (wg < 2) {
#pragma unroll
      for (int i = 0; i < 9; i++) {
        const uint2 v = lds2(sbase + O_MOD + (64 * i + 2 * l) * 4);
        ga[i] = __byte_perm(v.x, v.y, 0x7632);
        sh[i] = lds2(sbase + O_MOD + (D_ + 64 * i + 2 * l) * 4);
        sw[i] = lds2(sbase + O_MOD + (2 * D_ + 64 * i + 2 * l) * 4);
      }
    }
    wg_wait<0>();
    reg_fence(acc);
    CK(18);
#pragma unroll
    for (int i = 0; i < 3; i++) {
      const float* a = &acc[8 * i];
      const uint32_t a0 = pack_bf16(a[0], a[1]), a1 = pack_bf16(a[2], a[3]), a2 = pack_bf16(a[4], a[5]), a3 = pack_bf16(a[6], a[7]);
#pragma unroll
      for (int jh = 0; jh < 2; jh++) {
        float y[4];
        mma16<false>(y, a0, a1, a2, a3, tb[2 * jh], tb[2 * jh + 1]);
        sts(sy[2 * i] + jh * (4 * 584 * 4), pack_bf16(y[0], y[1]));
        sts(sy[2 * i + 1] + jh * (4 * 584 * 4), pack_bf16(y[2], y[3]));
      }
    }
    CK(19);
    if (wg == 2) bar_arrive(7, NTHR);
    else {
      bar_sync(7, NTHR);
      CK(20);
      float a[18], b[18];
#pragma unroll
      for (int i = 0; i < 9; i++) {
        const uint2 y = lds2(sbase + O_Y + (wp * 584 + 64 * i + 2 * l) * 4);
        xr[i] = hfma2(ga[i], __byte_perm(y.x, y.y, 0x5410), xr[i]);
        xr[9 + i] = hfma2(ga[i], __byte_perm(y.x, y.y, 0x7632), xr[9 + i]);
        a[2 * i] = bf_lo(xr[i]); a[2 * i + 1] = bf_hi(xr[i]); b[2 * i] = bf_lo(xr[9 + i]); b[2 * i + 1] = bf_hi(xr[9 + i]);
      }
      float oa, ra, ob, rb;
      ln_stats2(a, b, 1.0f, oa, ra, ob, rb);
      CK(21);
#pragma unroll
      for (int i = 0; i < 9; i++) {
        const float c0 = __uint_as_float(sw[i].x), c1 = __uint_as_float(sw[i].y), s0 = __uint_as_float(sh[i].x), s1 = __uint_as_float(sh[i].y);
        a[2 * i] = fmaf(fmaf(a[2 * i], ra, oa), c0, s0); a[2 * i + 1] = fmaf(fmaf(a[2 * i + 1], ra, oa), c1, s1);
        b[2 * i] = fmaf(fmaf(b[2 * i], rb, ob), c0, s0); b[2 * i + 1] = fmaf(fmaf(b[2 * i + 1], rb, ob), c1, s1);
      }
      ln_stats2(a, b, 0.5f, oa, ra, ob, rb);
      CK(22);
      const uint32_t sh3 = sbase + O_B3 + (wp >> 1) * 4608 + (l >> 4) * 256 + (wp & 1) * 128 + ((((l >> 2) ^ (2 * cta + (wp & 1))) & 3) << 4) + (l & 3) * 4;
#pragma unroll
      for (int i = 0; i < 9; i++) {
        sts(sh3 + i * 512, pack_bf16(fmaf(a[2 * i], ra, oa), fmaf(a[2 * i + 1], ra, oa)));
        sts(sh3 + i * 512 + 64, pack_bf16(fmaf(b[2 * i], rb, ob), fmaf(b[2 * i + 1], rb, ob)));
      }
      fence_async_smem();
      if (wp == 0) CKX(0);
      if (wp < 2 * H3G) bar_arrive(8, 32 + 64 * H3G); else bar_arrive(9, 288 - 64 * H3G);
      CK(23);
    }
  } else __syncthreads();

  const bool g2 = cta < 130 && (cta >> 1) != 56;
  const int z2 = cta < 112 ? cta : cta - 2, r = z2 >> 6;
  const int s2 = 128 * ((z2 >> 2) & 15), d2 = 144 * (z2 & 3);
  constexpr int XST = (33 + 36 - JSK - 1) % NST;
  constexpr int ST0 = (32 - JSK - 1) % NST, ST1 = 31 % NST;

  if (wg == 2) {
    asm volatile("setmaxnreg.dec.sync.aligned.u32 40;");
    if (wp == 8) {
      int st = rows ? 4 : 0, ph = 1;
#pragma unroll 1
      for (int kb = st; kb < 32; kb++) {
        if (rows && (kb >> 1) == 2) mbar_wait(full0 + 8 * (B_S4 - 4 + kb), 0);
        mbar_wait(empty0 + 8 * st, ph);
        if (elect()) {
          load_a1(st, kb);
          if (kb >= PF2K && kb < PF2K + PF2 && g2)
            prefetch_l2(reinterpret_cast<const uint8_t*>(p.w2) + (size_t)(36 * r + kb2_order(kb - PF2K)) * 262144 + (z2 & 63) * 4096, 4096);
        }
        __syncwarp();
        ring_next<false>(st, ph);
      }
      if (g2) {
        st++;
#pragma unroll 1
        for (int i = 0; i < 36; i++) {
          if (i == HOLDA) mbar_wait(full0 + 8 * B_GO, 0);
          mbar_wait(empty0 + 8 * st, ph);
          if (elect()) {
            mbar_expect(full0 + 8 * st, 16384 + 18432);
            tma3d_ef(sbase + st * STAGE, &maps.w2, 64 * (36 * r + kb2_order(i)), s2 >> 6, full0 + 8 * st);
          }
          __syncwarp();
          ring_next<true>(st, ph);
        }
      }
    } else if (wp >= 10) {
      const int sw = wp - 10;
      if (rows) {
        const CUtensorMap* mp = upin(&maps.h3[sw]);
        const uint32_t src = upin(sbase + O_B3 + sw * (H3G * 4608)), c0 = upin(64 * (cta & 15)), c1 = upin(18 * (cta >> 4)), c2 = upin(H3G * sw);
        unsigned* flag = pin(&sc->cnt[C_H3 + (cta >> 4) + 8 * sw]);
        bar_sync(8 + sw, sw ? 288 - 64 * H3G : 32 + 64 * H3G);
        if (!sw) CKX(1);
        if (sw) { mbar_wait(full0 + 8 * H3W, 0); CKX(7); }
        if (elect()) {
          tma_st3d(mp, src, c0, c1, c2);
          if (!sw) CKX(2);
          mbar_arrive(full0 + 8 * B_S4);
          bulk_commit_wait();
          if (!sw) CKX(3);
          mbar_arrive(full0 + 8 * B_S5);
          asm volatile("fence.acq_rel.gpu;" ::: "memory");
          red_add(flag, 1);
          if (!sw) CKX(4);
          TS(sw ? 24 : 13);
        }
        __syncwarp();
      }
      if (sw && g2) {
        mbar_wait(full0 + 8 * 5, 0);
#pragma unroll 1
        for (int i = 0; i < 36; i++) { sc->part[z2 * 1152 + 32 * i + l] = make_uint4(tag1 ^ 1, 0, 0, 0); __nanosleep(100); }
        __syncwarp();
      }
      const uint32_t stg = sbase + (sw ? ST1 : ST0) * STAGE;
      const int kbA = (f1 >> 6) + (helper ? 2 : 1) * (sw ^ flip), kbB = helper ? (f1 >> 6) + 1 : kbA;
      const int dB = helper ? d1 + 32 * sw : d1 + 96;
      uint8_t* const uA = upin(sc->u + ((size_t)kbA * D_ + d1) * 128);
      uint8_t* const uB = upin(sc->u + ((size_t)kbB * D_ + dB) * 128);
      unsigned* const fA = pin(&sc->cnt[C_U + kbA]);
      unsigned* const fB = pin(&sc->cnt[C_U + kbB]);
      bar_sync(11 + sw, 160);
      if (elect()) { bulk_st(uA, stg, 96 * 128); TS(sw ? 31 : 30); }
      __syncwarp();
      bar_sync(13 + sw, 160);
      if (elect()) {
        bulk_st(uB, stg + 96 * 128, helper ? 32 * 128 : 64 * 128);
        if (helper) bulk_st(uB + (64 - 16 * sw) * 128, stg + 128 * 128, 16 * 128);
        bulk_commit_wait();
        mbar_arrive(empty0 + 8 * (sw ? ST1 : ST0));
        if (sw == 0) TS(26);
        asm volatile("fence.acq_rel.gpu;" ::: "memory");
        red_add(fA, 2);
        if (helper) red_add(fB, 1);
        TS(sw ? 23 : 17);
      }
      __syncwarp();
    } else {
      uint64_t ready = 0;
      int st = 0, ph = 1;
#pragma unroll 1
      for (int kb = 0; kb < 32; kb++) {
        const uint8_t* src = upin(sc->h3 + ((size_t)(kb * 18 + (d1 >> 5)) << 12));
        const uint32_t dst = upin(sbase + st * STAGE + a1bytes);
        if (rows && (kb >> 1) == 2) mbar_wait(full0 + 8 * (B_S4 - 4 + kb), 0);
        mbar_wait(empty0 + 8 * st, ph);
        wait_flags(sc->cnt + C_H3, 32, (kb & 7) + (kb < 8 * H3G ? 0 : 8), 16 * ep, ready);
        if (kb == 0) CKX(5);
        if (elect()) bulk_ld(dst, src, STAGE - a1bytes, full0 + 8 * st);
        if (kb == 0) CKX(6);
        if (kb == 5) CKX(8);
        if (kb == 8 * H3G) CKX(9);
        ring_next<false>(st, ph);
      }
      if (g2) {
        ready = 0;
        st++;
#pragma unroll 1
        for (int i = 0; i < 72; i++) {
          if (i == 36) ready = 0;
          const int kb = kb2_order(i < 36 ? i : i - 36), hf = r ^ (i >= 36);
          const uint8_t* src = upin(sc->u + ((size_t)(36 * r + kb) * D_ + d2) * 128);
          const uint32_t dst = upin(sbase + st * STAGE + 16384);
          if (i <= 36) mbar_wait(empty0 + 8 * st, ph);
          wait_flags(sc->cnt + C_U + 36 * hf, 36, kb, 8 * ep, ready);
          if (i < 36) {
            if (elect()) {
              bulk_ld(dst, src, 18432, full0 + 8 * st);
              if (i == GOAT) mbar_arrive(full0 + 8 * B_GO);
            }
            ring_next<true>(st, ph);
          } else if (ready == ~0ull) break;
        }
        if (l == 0) mbar_expect(full0 + 8 * XST, 18432);
        __syncwarp();
        if (l < 3) tma2d(sbase + XST * STAGE + 18432 + l * 6144, &maps.x1, d2 + 48 * l, s2 + 64 * (r ^ 1), full0 + 8 * XST);
        __syncwarp();
      }
    }
  } else {
    asm volatile("setmaxnreg.inc.sync.aligned.u32 232;");
    const int wgu = wg;
    constexpr uint32_t sb4 = sbase >> 4;
    const int w = wp & 3;
    Ring rg = {0, 0};
    uint32_t* const x1p = sc->x1 + (size_t)(cta + 256 * wp) * 288 + l;
    float acc[80];
    constexpr uint32_t LA = (8192 >> 4) << 16, LB = (4096 >> 4) << 16;
    {
      const int fa = f1 + (helper ? 128 : 64) * (wg ^ flip) + 16 * w + g, fb = helper ? f1 + 64 + 16 * w + g : fa;
      const float a0 = 0.5f * __bfloat162float(p.b1[fa]), a1 = 0.5f * __bfloat162float(p.b1[fa + 8]);
      const float b0 = 0.5f * __bfloat162float(p.b1[fb]), b1 = 0.5f * __bfloat162float(p.b1[fb + 8]);
#pragma unroll
      for (int i = 0; i < 80; i++) acc[i] = i < 48 ? ((i & 2) ? a1 : a0) : ((i & 2) ? b1 : b0);
      reg_fence(acc);
    }
    if (!helper) gemm_main<0>(acc, sb4 + (wgu ^ flip) * 512 + LA, 0, sb4 + 1024 + LB, 0, wgu, rg, x1p, xr);
    else {
      float ac2[80];
#pragma unroll
      for (int i = 0; i < 72; i++) asm volatile("mov.b32 %0, %1;" : "=f"(ac2[i]) : "f"(acc[i]));
      gemm_main<1>(ac2, sb4 + (wgu ^ flip) * 1024 + LA, sb4 + 512 + LA, sb4 + 1536 + LB, sb4 + 1536 + (wgu ? 256 + LB + (2 << 16) : 2 * LB), wgu, rg, x1p, xr);
#pragma unroll
      for (int i = 0; i < 72; i++) asm volatile("mov.b32 %0, %1;" : "=f"(acc[i]) : "f"(ac2[i]));
    }
    if (t128 == 0) TS(wg ? 16 : 6);
    {
      const int mi = l >> 3, rr = l & 7;
      const uint32_t ad = sbase + (wg ? ST1 : ST0) * STAGE + (8 * (mi >> 1) + rr) * 128 + (((2 * w + (mi & 1)) ^ rr) << 4);
      float z[2][16];
#pragma unroll
      for (int j = -1; j <= 5; j++) {
        if (j >= 1) {
          const float* a = &acc[16 * (j - 1)];
          const float* tt = z[(j - 1) & 1];
#pragma unroll
          for (int h = 0; h < 16; h += 8)
            stmatrix4t(ad + (2 * (j - 1) + (h >> 3)) * 2048, pack_bf16(fmaf(a[h], tt[h], a[h]), fmaf(a[h + 1], tt[h + 1], a[h + 1])),
                       pack_bf16(fmaf(a[h + 2], tt[h + 2], a[h + 2]), fmaf(a[h + 3], tt[h + 3], a[h + 3])),
                       pack_bf16(fmaf(a[h + 4], tt[h + 4], a[h + 4]), fmaf(a[h + 5], tt[h + 5], a[h + 5])),
                       pack_bf16(fmaf(a[h + 6], tt[h + 6], a[h + 6]), fmaf(a[h + 7], tt[h + 7], a[h + 7])));
        }
        if (j >= 0 && j < 5) {
#pragma unroll
          for (int e = 0; e < 16; e++) asm("tanh.approx.f32 %0, %0;" : "+f"(z[j & 1][e]));
        }
        if (j < 4) {
#pragma unroll
          for (int e = 0; e < 16; e++) z[(j + 1) & 1][e] = gelu_arg(acc[16 * (j + 1) + e]);
        }
        if (j == 3 || j == 5) { fence_async_smem(); asm volatile("bar.arrive %0, 160;" ::"r"((j == 3 ? 11 : 13) + wgu) : "memory"); }
        if (j < 5) {
          if (j >= 0) reg_fence(z[j & 1]);
          if (j < 4) reg_fence(z[(j + 1) & 1]);
          if (__builtin_expect(wp == 0x7ffffff0 + j, 0)) __trap();
          reg_fence(acc);
        }
      }
      if (t128 == 0) TS(wg ? 29 : 28);
    }
    if (g2) {
      const int mb = wgu ^ r;
      uint32_t gb[18];
      {
        float a0 = 0.f, a1 = 0.f;
        if (wgu) {
          a0 = __bfloat162float(p.b2[s2 + 64 * mb + 16 * w + g]); a1 = __bfloat162float(p.b2[s2 + 64 * mb + 16 * w + 8 + g]);
          int it = 0;
          uint32_t bad;
          do {
            bad = 0;
#pragma unroll
            for (int i = 0; i < 18; i++) {
              const uint2 v = ld_rlx2(sc->mod + 3 * D_ + d2 + 8 * i + 2 * t);
              bad |= (v.x ^ tag16) | (v.y ^ tag16);
              gb[i] = __byte_perm(v.x, v.y, 0x7632);
            }
          } while (any(bad & 0xffffu) && ++it < SPIN_MAX);
        }
#pragma unroll
        for (int i = 0; i < 72; i++) acc[i] = (i & 2) ? a1 : a0;
      }
      rg.st++;
      gemm_main<3>(acc, sb4 + mb * 512 + LA, 0, sb4 + 1024 + (1 << 16), 0, wgu, rg, x1p, xr);
      if (t128 == 0) TS(wg ? 20 : 19);
      const uint32_t sx = sbase + XST * STAGE;
      if (wgu == 0) {
        uint4* dst = sc->part + z2 * 1152 + t128;
#pragma unroll
        for (int j = 0; j < 9; j++) {
          const float* a = &acc[8 * j];
          dst[j * 128] = make_uint4(set_tag(pack_bf16(a[0], a[1]), tag1), pack_bf16(a[2], a[3]), pack_bf16(a[4], a[5]), pack_bf16(a[6], a[7]));
        }
        if (tid == 0) TS(21);
        const uint4* src = sc->part + (z2 ^ 64) * 1152 + t128;
        uint4 v[9];
        uint32_t bad;
        int it = 0;
        do {
#pragma unroll
          for (int j = 0; j < 9; j++) v[j] = ld_rlx4(src + j * 128);
          bad = v[8].x ^ tag1;
#pragma unroll
          for (int j = 0; j < 8; j += 2) bad |= diff2(v[j].x, v[j + 1].x, tag1);
        } while (any(bad & 1) && ++it < SPIN_MAX);
#pragma unroll
        for (int j = 0; j < 9; j++) sts4(sx + t128 * 16 + j * 2048, v[j].x, v[j].y, v[j].z, v[j].w);
        bar_arrive(2 + w, 64);
        if (w == 0) {
#pragma unroll 1
          for (int i = 0; i < 3; i++) {
            bar_sync(11 + i, 160);
            if (elect()) tma_st2d(&maps.out, sx + 18432 + i * 6144, d2 + 48 * i, s2 + 64 * (r ^ 1));
            __syncwarp();
          }
          if (elect()) { bulk_commit_wait_read(); TS(22); }
          __syncwarp();
        }
      } else {
        mbar_wait(full0 + 8 * XST, rg.ph);
        bar_sync(2 + w, 64);
        if (t128 == 0) TS(5);
        if (tid == 128 && cta == 0) sc->cnt[C_EP] = ep;
        const uint32_t xa = sx + 18432 + (16 * w + (l & 15)) * 96 + (l >> 4) * 16;
#pragma unroll
        for (int c = 0; c < 3; c++) {
          uint32_t pv[3][4], xv[3][4];
#pragma unroll
          for (int j = 0; j < 3; j++) {
            asm volatile("ld.shared.v4.b32 {%0,%1,%2,%3}, [%4];" : "=r"(pv[j][0]), "=r"(pv[j][1]), "=r"(pv[j][2]), "=r"(pv[j][3]) : "r"(sx + t128 * 16 + (3 * c + j) * 2048) : "memory");
            asm volatile("ldmatrix.sync.aligned.m8n8.x4.shared.b16 {%0,%1,%2,%3}, [%4];" : "=r"(xv[j][0]), "=r"(xv[j][1]), "=r"(xv[j][2]), "=r"(xv[j][3]) : "r"(xa + c * 6144 + j * 32) : "memory");
          }
#pragma unroll
          for (int j = 0; j < 3; j++) {
            const float* a = &acc[8 * (3 * c + j)];
            uint32_t o[4];
#pragma unroll
            for (int e = 0; e < 4; e++)
              o[e] = hadd2(xv[j][e], hmul2(gb[2 * (3 * c + j) + (e >> 1)], pack_bf16(a[2 * e] + bf_lo(pv[j][e]), a[2 * e + 1] + bf_hi(pv[j][e]))));
            stmatrix4(xa + c * 6144 + j * 32, o[0], o[1], o[2], o[3]);
          }
          fence_async_smem();
          asm volatile("bar.arrive %0, 160;" ::"r"(11 + c) : "memory");
        }
        if (t128 == 0) TS(7);
        __syncwarp();
      }
    }
  }
}

typedef CUresult (*EncodeFn)(CUtensorMap*, CUtensorMapDataType, cuuint32_t, void*, const cuuint64_t*, const cuuint64_t*, const cuuint32_t*,
                             const cuuint32_t*, CUtensorMapInterleave, CUtensorMapSwizzle, CUtensorMapL2promotion, CUtensorMapFloatOOBfill);

struct Dim { cuuint64_t n, stride; cuuint32_t box; };
template <int RANK>
void make_map(EncodeFn enc, CUtensorMap* m, bool words, int swz, const void* ptr, const Dim (&d)[RANK]) {
  cuuint64_t gd[RANK], gs[RANK];
  cuuint32_t bx[RANK], es[RANK];
  for (int i = 0; i < RANK; i++) { gd[i] = d[i].n; gs[i] = d[i].stride; bx[i] = d[i].box; es[i] = 1; }
  enc(m, words ? CU_TENSOR_MAP_DATA_TYPE_UINT32 : CU_TENSOR_MAP_DATA_TYPE_BFLOAT16, RANK, const_cast<void*>(ptr), gd, gs + 1, bx, es,
      CU_TENSOR_MAP_INTERLEAVE_NONE, static_cast<CUtensorMapSwizzle>(swz),
      swz == 3 ? CU_TENSOR_MAP_L2_PROMOTION_L2_256B : CU_TENSOR_MAP_L2_PROMOTION_NONE, CU_TENSOR_MAP_FLOAT_OOB_FILL_NONE);
}

}

extern "C" void kernel_launch(void* const* d_in, const int* in_sizes, int n_in, void* d_out, int out_size) {
  (void)in_sizes; (void)n_in; (void)out_size;
  static EncodeFn enc = nullptr;
  static void *sptr = nullptr, *tptr = nullptr;
  if (!enc) {
    void* f = nullptr; cudaDriverEntryPointQueryResult qr;
    cudaGetDriverEntryPoint("cuTensorMapEncodeTiled", &f, cudaEnableDefault, &qr);
    enc = reinterpret_cast<EncodeFn>(f);
    cudaFuncSetAttribute(fused_kernel, cudaFuncAttributeMaxDynamicSharedMemorySize, SMEM_BYTES);
    cudaGetSymbolAddress(&sptr, g_s);
    cudaGetSymbolAddress(&tptr, T_TAB);
  }
  Params p;
  p.x = (const __nv_bfloat16*)d_in[0]; p.wr = (const __nv_bfloat16*)d_in[1]; p.wi = (const __nv_bfloat16*)d_in[2];
  p.b1 = (const __nv_bfloat16*)d_in[5]; p.b2 = (const __nv_bfloat16*)d_in[7];
  p.c = (const __nv_bfloat16*)d_in[8]; p.wmod = (const __nv_bfloat16*)d_in[9];
  p.w1 = (const __nv_bfloat16*)d_in[4]; p.w2 = (const __nv_bfloat16*)d_in[6];
  p.s = static_cast<Scratch*>(sptr); p.tab = static_cast<const uint4*>(tptr);
  Maps maps;
  make_map<4>(enc, &maps.w1a, false, 3, p.w1, {{64, 0, 64}, {16, 128 * 2 * F_, 4}, {128, 2 * F_, 16}, {72, 128, 2}});
  make_map<4>(enc, &maps.w1b, false, 3, p.w1, {{64, 0, 64}, {16, 128 * 2 * F_, 4}, {128, 2 * F_, 16}, {72, 128, 3}});
  make_map<3>(enc, &maps.w2, false, 3, p.w2, {{64, 0, 64}, {F_, 2 * S_, 64}, {32, 128, 2}});
  make_map<2>(enc, &maps.x1, false, 0, p.s->x1, {{D_, 0, 48}, {S_, 2 * D_, 64}});
  make_map<2>(enc, &maps.out, false, 0, d_out, {{D_, 0, 48}, {S_, 2 * D_, 64}});
  make_map<2>(enc, &maps.z1, true, 0, p.s->z1, {{5120, 0, 40}, {120, 20480, 60}});
  make_map<2>(enc, &maps.z2, true, 0, p.s->z2, {{4800, 0, 40}, {128, 19200, 128}});
  for (int i = 0; i < 4; i++) make_map<2>(enc, &maps.wf[i], false, 2 - (i & 1), (i & 2) ? p.wi : p.wr, {{16 * DF_, 0, (i & 1) ? 16u : 32u}, {128, 32 * DF_, 128}});
  make_map<2>(enc, &maps.wm, false, 1, p.wmod, {{6 * D_, 0, 16}, {D_, 12 * D_, 192}});
  for (int i = 0; i < 2; i++) make_map<3>(enc, &maps.h3[i], true, 0, p.s->h3, {{1024, 0, 64}, {144, 4096, 18}, {4, 144 * 4096, i ? 4u - H3G : H3G}});
  fused_kernel<<<NCTA, NTHR, SMEM_BYTES, cudaStreamPerThread>>>(p, maps);
}
```

```cpp
#include <cuda_runtime.h>
#include <cuda_bf16.h>
#include <cuda.h>
#include <stdint.h>

namespace {

constexpr int S_ = 2048, D_ = 576, DF_ = 289, F_ = 4608;
constexpr int NCTA = 132, NTHR = 384;
constexpr int STAGE = 36864, NST = 6;
constexpr uint32_t sbase = 1024, full0 = sbase + NST * STAGE, empty0 = full0 + 8 * NST, red = full0 + 256;
constexpr int SMEM_BYTES = NST * STAGE + 256 + 512 + 4 * D_ + 512;
constexpr int O_NRM = 0, O_B1 = 19456, O_Z1 = 38912, O_P2 = 59392;
constexpr int O_RAW = 4 * STAGE;
constexpr int O_IN = 4 * STAGE, O_Y = O_IN + 19456, O_B3 = O_IN + 38912, O_MOD = O_IN + 57344;

__device__ __align__(128) const uint32_t T_TAB[5632] = {
0x3f803f80,0xbf803f80,0x3f803f80,0xbf803f80,0x3f803f80,0xbf803f80,0x3f803f80,0xbf803f80,0x3f803f80,0xbf803f80,0x3f803f80,0xbf803f80,
0x3f803f80,0xbf803f80,0x3f803f80,0xbf803f80,0x3f7f3f80,0xbdc90000,0x3f223f35,0xbf46bf35,0x3f753f7b,0xbe95be48,0x3ef13f0e,0xbf62bf55,
0x3f623f6d,0xbef1bec4,0x3e953ec4,0xbf75bf6d,0x3f463f55,0xbf22bf0e,0x3dc93e48,0xbf7fbf7b,0x3f7b3f80,0xbe480000,0xbe480000,0xbf7bbf80,
0x3f553f6d,0xbf0ebec4,0xbf0ebec4,0xbf55bf6d,0x3f0e3f35,0xbf55bf35,0xbf55bf35,0xbf0ebf35,0x3e483ec4,0xbf7bbf6d,0xbf7bbf6d,0xbe48bec4,
0x3f753f80,0xbe950000,0xbf62bf35,0xbef1bf35,0x3f223f55,0xbf46bf0e,0xbf7fbf7b,0x3dc9be48,0x3dc93ec4,0xbf7fbf6d,0xbf46bf6d,0x3f223ec4,
0xbef1be48,0xbf62bf7b,0xbe95bf0e,0x3f753f55,0x3f6d3f80,0xbec40000,0xbf6dbf80,0x3ec40000,0x3ec43f35,0xbf6dbf35,0xbec4bf35,0x3f6d3f35,
0xbec40000,0xbf6dbf80,0x3ec40000,0x3f6d3f80,0xbf6dbf35,0xbec4bf35,0x3f6d3f35,0x3ec43f35,0x3f623f80,0xbef10000,0xbe95bf35,0x3f753f35,
0x3dc93f0e,0xbf7fbf55,0x3f223e48,0x3f463f7b,0xbf46bec4,0xbf22bf6d,0x3f7f3f6d,0xbdc93ec4,0xbf75bf7b,0x3e95be48,0x3ef13f55,0xbf62bf0e,
0x3f553f80,0xbf0e0000,0x3f0e0000,0x3f553f80,0xbe483ec4,0xbf7bbf6d,0x3f7b3f6d,0xbe483ec4,0xbf7bbf35,0xbe48bf35,0x3e483f35,0xbf7bbf35,
0xbf0ebf6d,0x3f553ec4,0xbf55bec4,0xbf0ebf6d,0x3f463f80,0xbf220000,0x3f7f3f35,0x3dc93f35,0xbef13e48,0xbf62bf7b,0x3e953f55,0xbf75bf0e,
0xbf75bf6d,0x3e95bec4,0xbf62bec4,0xbef1bf6d,0x3dc9bf0e,0x3f7f3f55,0xbf22bf7b,0x3f463e48,0x3f353f80,0xbf350000,0x3f353f80,0xbf350000,
0xbf350000,0xbf35bf80,0xbf350000,0xbf35bf80,0xbf35bf80,0x3f350000,0xbf35bf80,0x3f350000,0x3f350000,0x3f353f80,0x3f350000,0x3f353f80,
0x3f223f80,0xbf460000,0xbdc93f35,0xbf7fbf35,0xbf62be48,0xbef1bf7b,0xbf75bf55,0x3e95bf0e,0xbe95bf6d,0x3f753ec4,0x3ef1bec4,0x3f623f6d,
0x3f7f3f0e,0x3dc93f55,0x3f463f7b,0xbf223e48,0x3f0e3f80,0xbf550000,0xbf550000,0xbf0ebf80,0xbf7bbec4,0xbe48bf6d,0xbe48bf6d,0x3f7b3ec4,
0x3e48bf35,0x3f7b3f35,0x3f7b3f35,0xbe483f35,0x3f553f6d,0xbf0e3ec4,0xbf0e3ec4,0xbf55bf6d,0x3ef13f80,0xbf620000,0xbf75bf35,0x3e95bf35,
0xbf7fbf0e,0x3dc9bf55,0x3f46be48,0x3f223f7b,0x3f22bec4,0x3f463f6d,0x3dc93f6d,0xbf7fbec4,0x3e953f7b,0xbf75be48,0xbf62bf55,0x3ef1bf0e,
0x3ec43f80,0xbf6d0000,0xbec4bf80,0x3f6d0000,0xbf6dbf35,0x3ec4bf35,0x3f6d3f35,0xbec43f35,0x3f6d0000,0x3ec43f80,0xbf6d0000,0xbec4bf80,
0xbec43f35,0xbf6dbf35,0x3ec4bf35,0x3f6d3f35,0x3e953f80,0xbf750000,0x3ef1bf35,0x3f623f35,0xbf46bf55,0x3f22bf0e,0x3dc93f7b,0xbf7fbe48,
0x3f7f3ec4,0xbdc93f6d,0xbf22bf6d,0x3f46bec4,0xbf623e48,0xbef1bf7b,0x3f753f0e,0xbe953f55,0x3e483f80,0xbf7b0000,0x3f7b0000,0x3e483f80,
0xbf0ebf6d,0x3f55bec4,0xbf553ec4,0xbf0ebf6d,0x3f553f35,0xbf0e3f35,0x3f0ebf35,0x3f553f35,0xbf7bbec4,0x3e48bf6d,0xbe483f6d,0xbf7bbec4,
0x3dc93f80,0xbf7f0000,0x3f463f35,0xbf223f35,0xbe95bf7b,0x3f75be48,0xbf62bf0e,0x3ef1bf55,0x3ef13f6d,0xbf623ec4,0x3f753ec4,0xbe953f6d,
0xbf22bf55,0x3f46bf0e,0xbf7fbe48,0x3dc9bf7b,0x3f80,0xbf800000,0x3f80,0xbf800000,0xbf80,0x3f800000,0xbf80,0x3f800000,
0x3f80,0xbf800000,0x3f80,0xbf800000,0xbf80,0x3f800000,0xbf80,0x3f800000,0xbdc93f80,0xbf7f0000,0xbf463f35,0xbf22bf35,
0x3e95bf7b,0x3f753e48,0x3f62bf0e,0x3ef13f55,0xbef13f6d,0xbf62bec4,0xbf753ec4,0xbe95bf6d,0x3f22bf55,0x3f463f0e,0x3f7fbe48,0x3dc93f7b,
0xbe483f80,0xbf7b0000,0xbf7b0000,0x3e48bf80,0x3f0ebf6d,0x3f553ec4,0x3f553ec4,0xbf0e3f6d,0xbf553f35,0xbf0ebf35,0xbf0ebf35,0x3f55bf35,
0x3f7bbec4,0x3e483f6d,0x3e483f6d,0xbf7b3ec4,0xbe953f80,0xbf750000,0xbef1bf35,0x3f62bf35,0x3f46bf55,0x3f223f0e,0xbdc93f7b,0xbf7f3e48,
0xbf7f3ec4,0xbdc9bf6d,0x3f22bf6d,0x3f463ec4,0x3f623e48,0xbef13f7b,0xbf753f0e,0xbe95bf55,0xbec43f80,0xbf6d0000,0x3ec4bf80,0x3f6d0000,
0x3f6dbf35,0x3ec43f35,0xbf6d3f35,0xbec4bf35,0xbf6d0000,0x3ec4bf80,0x3f6d0000,0xbec43f80,0x3ec43f35,0xbf6d3f35,0xbec4bf35,0x3f6dbf35,
0xbef13f80,0xbf620000,0x3f75bf35,0x3e953f35,0x3f7fbf0e,0x3dc93f55,0xbf46be48,0x3f22bf7b,0xbf22bec4,0x3f46bf6d,0xbdc93f6d,0xbf7f3ec4,
0xbe953f7b,0xbf753e48,0x3f62bf55,0x3ef13f0e,0xbf0e3f80,0xbf550000,0x3f550000,0xbf0e3f80,0x3f7bbec4,0xbe483f6d,0x3e48bf6d,0x3f7bbec4,
0xbe48bf35,0x3f7bbf35,0xbf7b3f35,0xbe48bf35,0xbf553f6d,0xbf0ebec4,0x3f0e3ec4,0xbf553f6d,0xbf223f80,0xbf460000,0x3dc93f35,0xbf7f3f35,
0x3f62be48,0xbef13f7b,0x3f75bf55,0x3e953f0e,0x3e95bf6d,0x3f75bec4,0xbef1bec4,0x3f62bf6d,0xbf7f3f0e,0x3dc9bf55,0xbf463f7b,0xbf22be48,
0xbf353f80,0xbf350000,0xbf353f80,0xbf350000,0x3f350000,0xbf353f80,0x3f350000,0xbf353f80,0x3f35bf80,0x3f350000,0x3f35bf80,0x3f350000,
0xbf350000,0x3f35bf80,0xbf350000,0x3f35bf80,0xbf463f80,0xbf220000,0xbf7f3f35,0x3dc9bf35,0x3ef13e48,0xbf623f7b,0xbe953f55,0xbf753f0e,
0x3f75bf6d,0x3e953ec4,0x3f62bec4,0xbef13f6d,0xbdc9bf0e,0x3f7fbf55,0x3f22bf7b,0x3f46be48,0xbf553f80,0xbf0e0000,0xbf0e0000,0x3f55bf80,
0x3e483ec4,0xbf7b3f6d,0xbf7b3f6d,0xbe48bec4,0x3f7bbf35,0xbe483f35,0xbe483f35,0xbf7b3f35,0x3f0ebf6d,0x3f55bec4,0x3f55bec4,0xbf0e3f6d,
0xbf623f80,0xbef10000,0x3e95bf35,0x3f75bf35,0xbdc93f0e,0xbf7f3f55,0xbf223e48,0x3f46bf7b,0x3f46bec4,0xbf223f6d,0xbf7f3f6d,0xbdc9bec4,
0x3f75bf7b,0x3e953e48,0xbef13f55,0xbf623f0e,0xbf6d3f80,0xbec40000,0x3f6dbf80,0x3ec40000,0xbec43f35,0xbf6d3f35,0x3ec4bf35,0x3f6dbf35,
0x3ec40000,0xbf6d3f80,0xbec40000,0x3f6dbf80,0x3f6dbf35,0xbec43f35,0xbf6d3f35,0x3ec4bf35,0xbf753f80,0xbe950000,0x3f62bf35,0xbef13f35,
0xbf223f55,0xbf463f0e,0x3f7fbf7b,0x3dc93e48,0xbdc93ec4,0xbf7f3f6d,0x3f46bf6d,0x3f22bec4,0x3ef1be48,0xbf623f7b,0x3e95bf0e,0x3f75bf55,
0xbf7b3f80,0xbe480000,0x3e480000,0xbf7b3f80,0xbf553f6d,0xbf0e3ec4,0x3f0ebec4,0xbf553f6d,0xbf0e3f35,0xbf553f35,0x3f55bf35,0xbf0e3f35,
0xbe483ec4,0xbf7b3f6d,0x3f7bbf6d,0xbe483ec4,0xbf7f3f80,0xbdc90000,0xbf223f35,0xbf463f35,0xbf753f7b,0xbe953e48,0xbef13f0e,0xbf623f55,
0xbf623f6d,0xbef13ec4,0xbe953ec4,0xbf753f6d,0xbf463f55,0xbf223f0e,0xbdc93e48,0xbf7f3f7b,0x3f803f80,0xbf803f80,0x3f803f80,0xbf803f80,
0x3f803f80,0xbf803f80,0x3f803f80,0xbf803f80,0x3f803f80,0xbf803f80,0x3f803f80,0xbf803f80,0x3f803f80,0xbf803f80,0x3f803f80,0xbf803f80,
0xbdc90000,0xbf7fbf80,0xbf46bf35,0xbf22bf35,0xbe95be48,0xbf75bf7b,0xbf62bf55,0xbef1bf0e,0xbef1bec4,0xbf62bf6d,0xbf75bf6d,0xbe95bec4,
0xbf22bf0e,0xbf46bf55,0xbf7fbf7b,0xbdc9be48,0xbf7bbf80,0x3e480000,0x3e480000,0x3f7b3f80,0xbf55bf6d,0x3f0e3ec4,0x3f0e3ec4,0x3f553f6d,
0xbf0ebf35,0x3f553f35,0x3f553f35,0x3f0e3f35,0xbe48bec4,0x3f7b3f6d,0x3f7b3f6d,0x3e483ec4,0x3e950000,0x3f753f80,0x3ef13f35,0xbf62bf35,
0x3f463f0e,0x3f223f55,0xbdc93e48,0xbf7fbf7b,0x3f7f3f6d,0x3dc93ec4,0xbf22bec4,0xbf46bf6d,0x3f623f7b,0xbef1be48,0xbf75bf55,0xbe95bf0e,
0x3f6d3f80,0xbec40000,0xbf6dbf80,0x3ec40000,0x3ec43f35,0xbf6dbf35,0xbec4bf35,0x3f6d3f35,0xbec40000,0xbf6dbf80,0x3ec40000,0x3f6d3f80,
0xbf6dbf35,0xbec4bf35,0x3f6d3f35,0x3ec43f35,0xbef10000,0xbf62bf80,0x3f753f35,0x3e953f35,0xbf7fbf55,0xbdc9bf0e,0x3f463f7b,0xbf22be48,
0xbf22bf6d,0x3f463ec4,0xbdc93ec4,0xbf7fbf6d,0x3e95be48,0x3f753f7b,0xbf62bf0e,0xbef1bf55,0xbf55bf80,0x3f0e0000,0xbf0e0000,0xbf55bf80,
0x3e48bec4,0x3f7b3f6d,0xbf7bbf6d,0x3e48bec4,0x3f7b3f35,0x3e483f35,0xbe48bf35,0x3f7b3f35,0x3f0e3f6d,0xbf55bec4,0x3f553ec4,0x3f0e3f6d,
0x3f220000,0x3f463f80,0xbdc9bf35,0x3f7f3f35,0x3f623f7b,0xbef13e48,0x3f753f0e,0x3e953f55,0xbe953ec4,0xbf75bf6d,0x3ef13f6d,0xbf62bec4,
0xbf7fbf55,0x3dc9bf0e,0xbf46be48,0xbf22bf7b,0x3f353f80,0xbf350000,0x3f353f80,0xbf350000,0xbf350000,0xbf35bf80,0xbf350000,0xbf35bf80,
0xbf35bf80,0x3f350000,0xbf35bf80,0x3f350000,0x3f350000,0x3f353f80,0x3f350000,0x3f353f80,0xbf460000,0xbf22bf80,0xbf7fbf35,0x3dc9bf35,
0xbef1bf7b,0x3f623e48,0x3e95bf0e,0x3f753f55,0x3f753ec4,0x3e953f6d,0x3f623f6d,0xbef13ec4,0x3dc93f55,0xbf7fbf0e,0xbf223e48,0xbf46bf7b,
0xbf0ebf80,0x3f550000,0x3f550000,0x3f0e3f80,0x3f7b3ec4,0x3e483f6d,0x3e483f6d,0xbf7bbec4,0xbe483f35,0xbf7bbf35,0xbf7bbf35,0x3e48bf35,
0xbf55bf6d,0x3f0ebec4,0x3f0ebec4,0x3f553f6d,0x3f620000,0x3ef13f80,0xbe953f35,0xbf75bf35,0xbdc93f55,0xbf7fbf0e,0xbf22bf7b,0x3f46be48,
0xbf46bf6d,0x3f22bec4,0x3f7f3ec4,0x3dc93f6d,0x3f753e48,0x3e953f7b,0xbef13f0e,0xbf62bf55,0x3ec43f80,0xbf6d0000,0xbec4bf80,0x3f6d0000,
0xbf6dbf35,0x3ec4bf35,0x3f6d3f35,0xbec43f35,0x3f6d0000,0x3ec43f80,0xbf6d0000,0xbec4bf80,0xbec43f35,0xbf6dbf35,0x3ec4bf35,0x3f6d3f35,
0xbf750000,0xbe95bf80,0x3f623f35,0xbef13f35,0x3f22bf0e,0x3f463f55,0xbf7fbe48,0xbdc9bf7b,0xbdc93f6d,0xbf7fbec4,0x3f46bec4,0x3f223f6d,
0xbef1bf7b,0x3f62be48,0xbe953f55,0xbf75bf0e,0xbe48bf80,0x3f7b0000,0xbf7b0000,0xbe48bf80,0x3f0e3f6d,0xbf553ec4,0x3f55bec4,0x3f0e3f6d,
0xbf55bf35,0x3f0ebf35,0xbf0e3f35,0xbf55bf35,0x3f7b3ec4,0xbe483f6d,0x3e48bf6d,0x3f7b3ec4,0x3f7f0000,0x3dc93f80,0x3f22bf35,0x3f463f35,
0xbf753e48,0xbe95bf7b,0xbef13f55,0xbf62bf0e,0x3f62bec4,0x3ef13f6d,0x3e95bf6d,0x3f753ec4,0xbf463f0e,0xbf22bf55,0xbdc93f7b,0xbf7fbe48,
0x3f80,0xbf800000,0x3f80,0xbf800000,0xbf80,0x3f800000,0xbf80,0x3f800000,0x3f80,0xbf800000,0x3f80,0xbf800000,
0xbf80,0x3f800000,0xbf80,0x3f800000,0xbf7f0000,0x3dc9bf80,0xbf22bf35,0x3f46bf35,0x3f753e48,0xbe953f7b,0x3ef13f55,0xbf623f0e,
0xbf62bec4,0x3ef1bf6d,0xbe95bf6d,0x3f75bec4,0x3f463f0e,0xbf223f55,0x3dc93f7b,0xbf7f3e48,0x3e48bf80,0x3f7b0000,0x3f7b0000,0xbe483f80,
0xbf0e3f6d,0xbf55bec4,0xbf55bec4,0x3f0ebf6d,0x3f55bf35,0x3f0e3f35,0x3f0e3f35,0xbf553f35,0xbf7b3ec4,0xbe48bf6d,0xbe48bf6d,0x3f7bbec4,
0x3f750000,0xbe953f80,0xbf623f35,0xbef1bf35,0xbf22bf0e,0x3f46bf55,0x3f7fbe48,0xbdc93f7b,0x3dc93f6d,0xbf7f3ec4,0xbf46bec4,0x3f22bf6d,
0x3ef1bf7b,0x3f623e48,0x3e953f55,0xbf753f0e,0xbec43f80,0xbf6d0000,0x3ec4bf80,0x3f6d0000,0x3f6dbf35,0x3ec43f35,0xbf6d3f35,0xbec4bf35,
0xbf6d0000,0x3ec4bf80,0x3f6d0000,0xbec43f80,0x3ec43f35,0xbf6d3f35,0xbec4bf35,0x3f6dbf35,0xbf620000,0x3ef1bf80,0x3e953f35,0xbf753f35,
0x3dc93f55,0xbf7f3f0e,0x3f22bf7b,0x3f463e48,0x3f46bf6d,0x3f223ec4,0xbf7f3ec4,0x3dc9bf6d,0xbf753e48,0x3e95bf7b,0x3ef13f0e,0xbf623f55,
0x3f0ebf80,0x3f550000,0xbf550000,0x3f0ebf80,0xbf7b3ec4,0x3e48bf6d,0xbe483f6d,0xbf7b3ec4,0x3e483f35,0xbf7b3f35,0x3f7bbf35,0x3e483f35,
0x3f55bf6d,0x3f0e3ec4,0xbf0ebec4,0x3f55bf6d,0x3f460000,0xbf223f80,0x3f7fbf35,0x3dc93f35,0x3ef1bf7b,0x3f62be48,0xbe95bf0e,0x3f75bf55,
0xbf753ec4,0x3e95bf6d,0xbf623f6d,0xbef1bec4,0xbdc93f55,0xbf7f3f0e,0x3f223e48,0xbf463f7b,0xbf353f80,0xbf350000,0xbf353f80,0xbf350000,
0x3f350000,0xbf353f80,0x3f350000,0xbf353f80,0x3f35bf80,0x3f350000,0x3f35bf80,0x3f350000,0xbf350000,0x3f35bf80,0xbf350000,0x3f35bf80,
0xbf220000,0x3f46bf80,0x3dc9bf35,0x3f7fbf35,0xbf623f7b,0xbef1be48,0xbf753f0e,0x3e95bf55,0x3e953ec4,0xbf753f6d,0xbef13f6d,0xbf623ec4,
0x3f7fbf55,0x3dc93f0e,0x3f46be48,0xbf223f7b,0x3f55bf80,0x3f0e0000,0x3f0e0000,0xbf553f80,0xbe48bec4,0x3f7bbf6d,0x3f7bbf6d,0x3e483ec4,
0xbf7b3f35,0x3e48bf35,0x3e48bf35,0x3f7bbf35,0xbf0e3f6d,0xbf553ec4,0xbf553ec4,0x3f0ebf6d,0x3ef10000,0xbf623f80,0xbf753f35,0x3e95bf35,
0x3f7fbf55,0xbdc93f0e,0xbf463f7b,0xbf223e48,0x3f22bf6d,0x3f46bec4,0x3dc93ec4,0xbf7f3f6d,0xbe95be48,0x3f75bf7b,0x3f62bf0e,0xbef13f55,
0xbf6d3f80,0xbec40000,0x3f6dbf80,0x3ec40000,0xbec43f35,0xbf6d3f35,0x3ec4bf35,0x3f6dbf35,0x3ec40000,0xbf6d3f80,0xbec40000,0x3f6dbf80,
0x3f6dbf35,0xbec43f35,0xbf6d3f35,0x3ec4bf35,0xbe950000,0x3f75bf80,0xbef13f35,0xbf623f35,0xbf463f0e,0x3f22bf55,0x3dc93e48,0xbf7f3f7b,
0xbf7f3f6d,0x3dc9bec4,0x3f22bec4,0xbf463f6d,0xbf623f7b,0xbef13e48,0x3f75bf55,0xbe953f0e,0x3f7bbf80,0x3e480000,0xbe480000,0x3f7bbf80,
0x3f55bf6d,0x3f0ebec4,0xbf0e3ec4,0x3f55bf6d,0x3f0ebf35,0x3f55bf35,0xbf553f35,0x3f0ebf35,0x3e48bec4,0x3f7bbf6d,0xbf7b3f6d,0x3e48bec4,
0x3dc90000,0xbf7f3f80,0x3f46bf35,0xbf223f35,0x3e95be48,0xbf753f7b,0x3f62bf55,0xbef13f0e,0x3ef1bec4,0xbf623f6d,0x3f75bf6d,0xbe953ec4,
0x3f22bf0e,0xbf463f55,0x3f7fbf7b,0xbdc93e48,0x3f803f80,0xbf803f80,0x3f803f80,0xbf803f80,0x3f803f80,0xbf803f80,0x3f803f80,0xbf803f80,
0x3f803f80,0xbf803f80,0x3f803f80,0xbf803f80,0x3f803f80,0xbf803f80,0x3f803f80,0xbf803f80,0xbf7fbf80,0x3dc90000,0xbf22bf35,0x3f463f35,
0xbf75bf7b,0x3e953e48,0xbef1bf0e,0x3f623f55,0xbf62bf6d,0x3ef13ec4,0xbe95bec4,0x3f753f6d,0xbf46bf55,0x3f223f0e,0xbdc9be48,0x3f7f3f7b,
0x3f7b3f80,0xbe480000,0xbe480000,0xbf7bbf80,0x3f553f6d,0xbf0ebec4,0xbf0ebec4,0xbf55bf6d,0x3f0e3f35,0xbf55bf35,0xbf55bf35,0xbf0ebf35,
0x3e483ec4,0xbf7bbf6d,0xbf7bbf6d,0xbe48bec4,0xbf75bf80,0x3e950000,0x3f623f35,0x3ef13f35,0xbf22bf55,0x3f463f0e,0x3f7f3f7b,0xbdc93e48,
0xbdc9bec4,0x3f7f3f6d,0x3f463f6d,0xbf22bec4,0x3ef13e48,0x3f623f7b,0x3e953f0e,0xbf75bf55,0x3f6d3f80,0xbec40000,0xbf6dbf80,0x3ec40000,
0x3ec43f35,0xbf6dbf35,0xbec4bf35,0x3f6d3f35,0xbec40000,0xbf6dbf80,0x3ec40000,0x3f6d3f80,0xbf6dbf35,0xbec4bf35,0x3f6d3f35,0x3ec43f35,
0xbf62bf80,0x3ef10000,0x3e953f35,0xbf75bf35,0xbdc9bf0e,0x3f7f3f55,0xbf22be48,0xbf46bf7b,0x3f463ec4,0x3f223f6d,0xbf7fbf6d,0x3dc9bec4,
0x3f753f7b,0xbe953e48,0xbef1bf55,0x3f623f0e,0x3f553f80,0xbf0e0000,0x3f0e0000,0x3f553f80,0xbe483ec4,0xbf7bbf6d,0x3f7b3f6d,0xbe483ec4,
0xbf7bbf35,0xbe48bf35,0x3e483f35,0xbf7bbf35,0xbf0ebf6d,0x3f553ec4,0xbf55bec4,0xbf0ebf6d,0xbf46bf80,0x3f220000,0xbf7fbf35,0xbdc9bf35,
0x3ef1be48,0x3f623f7b,0xbe95bf55,0x3f753f0e,0x3f753f6d,0xbe953ec4,0x3f623ec4,0x3ef13f6d,0xbdc93f0e,0xbf7fbf55,0x3f223f7b,0xbf46be48,
0x3f353f80,0xbf350000,0x3f353f80,0xbf350000,0xbf350000,0xbf35bf80,0xbf350000,0xbf35bf80,0xbf35bf80,0x3f350000,0xbf35bf80,0x3f350000,
0x3f350000,0x3f353f80,0x3f350000,0x3f353f80,0xbf22bf80,0x3f460000,0x3dc9bf35,0x3f7f3f35,0x3f623e48,0x3ef13f7b,0x3f753f55,0xbe953f0e,
0x3e953f6d,0xbf75bec4,0xbef13ec4,0xbf62bf6d,0xbf7fbf0e,0xbdc9bf55,0xbf46bf7b,0x3f22be48,0x3f0e3f80,0xbf550000,0xbf550000,0xbf0ebf80,
0xbf7bbec4,0xbe48bf6d,0xbe48bf6d,0x3f7b3ec4,0x3e48bf35,0x3f7b3f35,0x3f7b3f35,0xbe483f35,0x3f553f6d,0xbf0e3ec4,0xbf0e3ec4,0xbf55bf6d,
0xbef1bf80,0x3f620000,0x3f753f35,0xbe953f35,0x3f7f3f0e,0xbdc93f55,0xbf463e48,0xbf22bf7b,0xbf223ec4,0xbf46bf6d,0xbdc9bf6d,0x3f7f3ec4,
0xbe95bf7b,0x3f753e48,0x3f623f55,0xbef13f0e,0x3ec43f80,0xbf6d0000,0xbec4bf80,0x3f6d0000,0xbf6dbf35,0x3ec4bf35,0x3f6d3f35,0xbec43f35,
0x3f6d0000,0x3ec43f80,0xbf6d0000,0xbec4bf80,0xbec43f35,0xbf6dbf35,0x3ec4bf35,0x3f6d3f35,0xbe95bf80,0x3f750000,0xbef13f35,0xbf62bf35,
0x3f463f55,0xbf223f0e,0xbdc9bf7b,0x3f7f3e48,0xbf7fbec4,0x3dc9bf6d,0x3f223f6d,0xbf463ec4,0x3f62be48,0x3ef13f7b,0xbf75bf0e,0x3e95bf55,
0x3e483f80,0xbf7b0000,0x3f7b0000,0x3e483f80,0xbf0ebf6d,0x3f55bec4,0xbf553ec4,0xbf0ebf6d,0x3f553f35,0xbf0e3f35,0x3f0ebf35,0x3f553f35,
0xbf7bbec4,0x3e48bf6d,0xbe483f6d,0xbf7bbec4,0xbdc9bf80,0x3f7f0000,0xbf46bf35,0x3f22bf35,0x3e953f7b,0xbf753e48,0x3f623f0e,0xbef13f55,
0xbef1bf6d,0x3f62bec4,0xbf75bec4,0x3e95bf6d,0x3f223f55,0xbf463f0e,0x3f7f3e48,0xbdc93f7b,0x3f80,0xbf800000,0x3f80,0xbf800000,
0xbf80,0x3f800000,0xbf80,0x3f800000,0x3f80,0xbf800000,0x3f80,0xbf800000,0xbf80,0x3f800000,0xbf80,0x3f800000,
0x3dc9bf80,0x3f7f0000,0x3f46bf35,0x3f223f35,0xbe953f7b,0xbf75be48,0xbf623f0e,0xbef1bf55,0x3ef1bf6d,0x3f623ec4,0x3f75bec4,0x3e953f6d,
0xbf223f55,0xbf46bf0e,0xbf7f3e48,0xbdc9bf7b,0xbe483f80,0xbf7b0000,0xbf7b0000,0x3e48bf80,0x3f0ebf6d,0x3f553ec4,0x3f553ec4,0xbf0e3f6d,
0xbf553f35,0xbf0ebf35,0xbf0ebf35,0x3f55bf35,0x3f7bbec4,0x3e483f6d,0x3e483f6d,0xbf7b3ec4,0x3e95bf80,0x3f750000,0x3ef13f35,0xbf623f35,
0xbf463f55,0xbf22bf0e,0x3dc9bf7b,0x3f7fbe48,0x3f7fbec4,0x3dc93f6d,0xbf223f6d,0xbf46bec4,0xbf62be48,0x3ef1bf7b,0x3f75bf0e,0x3e953f55,
0xbec43f80,0xbf6d0000,0x3ec4bf80,0x3f6d0000,0x3f6dbf35,0x3ec43f35,0xbf6d3f35,0xbec4bf35,0xbf6d0000,0x3ec4bf80,0x3f6d0000,0xbec43f80,
0x3ec43f35,0xbf6d3f35,0xbec4bf35,0x3f6dbf35,0x3ef1bf80,0x3f620000,0xbf753f35,0xbe95bf35,0xbf7f3f0e,0xbdc9bf55,0x3f463e48,0xbf223f7b,
0x3f223ec4,0xbf463f6d,0x3dc9bf6d,0x3f7fbec4,0x3e95bf7b,0x3f75be48,0xbf623f55,0xbef1bf0e,0xbf0e3f80,0xbf550000,0x3f550000,0xbf0e3f80,
0x3f7bbec4,0xbe483f6d,0x3e48bf6d,0x3f7bbec4,0xbe48bf35,0x3f7bbf35,0xbf7b3f35,0xbe48bf35,0xbf553f6d,0xbf0ebec4,0x3f0e3ec4,0xbf553f6d,
0x3f22bf80,0x3f460000,0xbdc9bf35,0x3f7fbf35,0xbf623e48,0x3ef1bf7b,0xbf753f55,0xbe95bf0e,0xbe953f6d,0xbf753ec4,0x3ef13ec4,0xbf623f6d,
0x3f7fbf0e,0xbdc93f55,0x3f46bf7b,0x3f223e48,0xbf353f80,0xbf350000,0xbf353f80,0xbf350000,0x3f350000,0xbf353f80,0x3f350000,0xbf353f80,
0x3f35bf80,0x3f350000,0x3f35bf80,0x3f350000,0xbf350000,0x3f35bf80,0xbf350000,0x3f35bf80,0x3f46bf80,0x3f220000,0x3f7fbf35,0xbdc93f35,
0xbef1be48,0x3f62bf7b,0x3e95bf55,0x3f75bf0e,0xbf753f6d,0xbe95bec4,0xbf623ec4,0x3ef1bf6d,0x3dc93f0e,0xbf7f3f55,0xbf223f7b,0xbf463e48,
0xbf553f80,0xbf0e0000,0xbf0e0000,0x3f55bf80,0x3e483ec4,0xbf7b3f6d,0xbf7b3f6d,0xbe48bec4,0x3f7bbf35,0xbe483f35,0xbe483f35,0xbf7b3f35,
0x3f0ebf6d,0x3f55bec4,0x3f55bec4,0xbf0e3f6d,0x3f62bf80,0x3ef10000,0xbe953f35,0xbf753f35,0x3dc9bf0e,0x3f7fbf55,0x3f22be48,0xbf463f7b,
0xbf463ec4,0x3f22bf6d,0x3f7fbf6d,0x3dc93ec4,0xbf753f7b,0xbe95be48,0x3ef1bf55,0x3f62bf0e,0xbf6d3f80,0xbec40000,0x3f6dbf80,0x3ec40000,
0xbec43f35,0xbf6d3f35,0x3ec4bf35,0x3f6dbf35,0x3ec40000,0xbf6d3f80,0xbec40000,0x3f6dbf80,0x3f6dbf35,0xbec43f35,0xbf6d3f35,0x3ec4bf35,
0x3f75bf80,0x3e950000,0xbf623f35,0x3ef1bf35,0x3f22bf55,0x3f46bf0e,0xbf7f3f7b,0xbdc9be48,0x3dc9bec4,0x3f7fbf6d,0xbf463f6d,0xbf223ec4,
0xbef13e48,0x3f62bf7b,0xbe953f0e,0xbf753f55,0xbf7b3f80,0xbe480000,0x3e480000,0xbf7b3f80,0xbf553f6d,0xbf0e3ec4,0x3f0ebec4,0xbf553f6d,
0xbf0e3f35,0xbf553f35,0x3f55bf35,0xbf0e3f35,0xbe483ec4,0xbf7b3f6d,0x3f7bbf6d,0xbe483ec4,0x3f7fbf80,0x3dc90000,0x3f22bf35,0x3f46bf35,
0x3f75bf7b,0x3e95be48,0x3ef1bf0e,0x3f62bf55,0x3f62bf6d,0x3ef1bec4,0x3e95bec4,0x3f75bf6d,0x3f46bf55,0x3f22bf0e,0x3dc9be48,0x3f7fbf7b,
0x3f803f80,0xbf803f80,0x3f803f80,0xbf803f80,0x3f803f80,0xbf803f80,0x3f803f80,0xbf803f80,0x3f803f80,0xbf803f80,0x3f803f80,0xbf803f80,
0x3f803f80,0xbf803f80,0x3f803f80,0xbf803f80,0x3dc90000,0x3f7f3f80,0x3f463f35,0x3f223f35,0x3e953e48,0x3f753f7b,0x3f623f55,0x3ef13f0e,
0x3ef13ec4,0x3f623f6d,0x3f753f6d,0x3e953ec4,0x3f223f0e,0x3f463f55,0x3f7f3f7b,0x3dc93e48,0xbf7bbf80,0x3e480000,0x3e480000,0x3f7b3f80,
0xbf55bf6d,0x3f0e3ec4,0x3f0e3ec4,0x3f553f6d,0xbf0ebf35,0x3f553f35,0x3f553f35,0x3f0e3f35,0xbe48bec4,0x3f7b3f6d,0x3f7b3f6d,0x3e483ec4,
0xbe950000,0xbf75bf80,0xbef1bf35,0x3f623f35,0xbf46bf0e,0xbf22bf55,0x3dc9be48,0x3f7f3f7b,0xbf7fbf6d,0xbdc9bec4,0x3f223ec4,0x3f463f6d,
0xbf62bf7b,0x3ef13e48,0x3f753f55,0x3e953f0e,0x3f6d3f80,0xbec40000,0xbf6dbf80,0x3ec40000,0x3ec43f35,0xbf6dbf35,0xbec4bf35,0x3f6d3f35,
0xbec40000,0xbf6dbf80,0x3ec40000,0x3f6d3f80,0xbf6dbf35,0xbec4bf35,0x3f6d3f35,0x3ec43f35,0x3ef10000,0x3f623f80,0xbf75bf35,0xbe95bf35,
0x3f7f3f55,0x3dc93f0e,0xbf46bf7b,0x3f223e48,0x3f223f6d,0xbf46bec4,0x3dc9bec4,0x3f7f3f6d,0xbe953e48,0xbf75bf7b,0x3f623f0e,0x3ef13f55,
0xbf55bf80,0x3f0e0000,0xbf0e0000,0xbf55bf80,0x3e48bec4,0x3f7b3f6d,0xbf7bbf6d,0x3e48bec4,0x3f7b3f35,0x3e483f35,0xbe48bf35,0x3f7b3f35,
0x3f0e3f6d,0xbf55bec4,0x3f553ec4,0x3f0e3f6d,0xbf220000,0xbf46bf80,0x3dc93f35,0xbf7fbf35,0xbf62bf7b,0x3ef1be48,0xbf75bf0e,0xbe95bf55,
0x3e95bec4,0x3f753f6d,0xbef1bf6d,0x3f623ec4,0x3f7f3f55,0xbdc93f0e,0x3f463e48,0x3f223f7b,0x3f353f80,0xbf350000,0x3f353f80,0xbf350000,
0xbf350000,0xbf35bf80,0xbf350000,0xbf35bf80,0xbf35bf80,0x3f350000,0xbf35bf80,0x3f350000,0x3f350000,0x3f353f80,0x3f350000,0x3f353f80,
0x3f460000,0x3f223f80,0x3f7f3f35,0xbdc93f35,0x3ef13f7b,0xbf62be48,0xbe953f0e,0xbf75bf55,0xbf75bec4,0xbe95bf6d,0xbf62bf6d,0x3ef1bec4,
0xbdc9bf55,0x3f7f3f0e,0x3f22be48,0x3f463f7b,0xbf0ebf80,0x3f550000,0x3f550000,0x3f0e3f80,0x3f7b3ec4,0x3e483f6d,0x3e483f6d,0xbf7bbec4,
0xbe483f35,0xbf7bbf35,0xbf7bbf35,0x3e48bf35,0xbf55bf6d,0x3f0ebec4,0x3f0ebec4,0x3f553f6d,0xbf620000,0xbef1bf80,0x3e95bf35,0x3f753f35,
0x3dc9bf55,0x3f7f3f0e,0x3f223f7b,0xbf463e48,0x3f463f6d,0xbf223ec4,0xbf7fbec4,0xbdc9bf6d,0xbf75be48,0xbe95bf7b,0x3ef1bf0e,0x3f623f55,
0x3ec43f80,0xbf6d0000,0xbec4bf80,0x3f6d0000,0xbf6dbf35,0x3ec4bf35,0x3f6d3f35,0xbec43f35,0x3f6d0000,0x3ec43f80,0xbf6d0000,0xbec4bf80,
0xbec43f35,0xbf6dbf35,0x3ec4bf35,0x3f6d3f35,0x3f750000,0x3e953f80,0xbf62bf35,0x3ef1bf35,0xbf223f0e,0xbf46bf55,0x3f7f3e48,0x3dc93f7b,
0x3dc9bf6d,0x3f7f3ec4,0xbf463ec4,0xbf22bf6d,0x3ef13f7b,0xbf623e48,0x3e95bf55,0x3f753f0e,0xbe48bf80,0x3f7b0000,0xbf7b0000,0xbe48bf80,
0x3f0e3f6d,0xbf553ec4,0x3f55bec4,0x3f0e3f6d,0xbf55bf35,0x3f0ebf35,0xbf0e3f35,0xbf55bf35,0x3f7b3ec4,0xbe483f6d,0x3e48bf6d,0x3f7b3ec4,
0xbf7f0000,0xbdc9bf80,0xbf223f35,0xbf46bf35,0x3f75be48,0x3e953f7b,0x3ef1bf55,0x3f623f0e,0xbf623ec4,0xbef1bf6d,0xbe953f6d,0xbf75bec4,
0x3f46bf0e,0x3f223f55,0x3dc9bf7b,0x3f7f3e48,0x3f80,0xbf800000,0x3f80,0xbf800000,0xbf80,0x3f800000,0xbf80,0x3f800000,
0x3f80,0xbf800000,0x3f80,0xbf800000,0xbf80,0x3f800000,0xbf80,0x3f800000,0x3f7f0000,0xbdc93f80,0x3f223f35,0xbf463f35,
0xbf75be48,0x3e95bf7b,0xbef1bf55,0x3f62bf0e,0x3f623ec4,0xbef13f6d,0x3e953f6d,0xbf753ec4,0xbf46bf0e,0x3f22bf55,0xbdc9bf7b,0x3f7fbe48,
0x3e48bf80,0x3f7b0000,0x3f7b0000,0xbe483f80,0xbf0e3f6d,0xbf55bec4,0xbf55bec4,0x3f0ebf6d,0x3f55bf35,0x3f0e3f35,0x3f0e3f35,0xbf553f35,
0xbf7b3ec4,0xbe48bf6d,0xbe48bf6d,0x3f7bbec4,0xbf750000,0x3e95bf80,0x3f62bf35,0x3ef13f35,0x3f223f0e,0xbf463f55,0xbf7f3e48,0x3dc9bf7b,
0xbdc9bf6d,0x3f7fbec4,0x3f463ec4,0xbf223f6d,0xbef13f7b,0xbf62be48,0xbe95bf55,0x3f75bf0e,0xbec43f80,0xbf6d0000,0x3ec4bf80,0x3f6d0000,
0x3f6dbf35,0x3ec43f35,0xbf6d3f35,0xbec4bf35,0xbf6d0000,0x3ec4bf80,0x3f6d0000,0xbec43f80,0x3ec43f35,0xbf6d3f35,0xbec4bf35,0x3f6dbf35,
0x3f620000,0xbef13f80,0xbe95bf35,0x3f75bf35,0xbdc9bf55,0x3f7fbf0e,0xbf223f7b,0xbf46be48,0xbf463f6d,0xbf22bec4,0x3f7fbec4,0xbdc93f6d,
0x3f75be48,0xbe953f7b,0xbef1bf0e,0x3f62bf55,0x3f0ebf80,0x3f550000,0xbf550000,0x3f0ebf80,0xbf7b3ec4,0x3e48bf6d,0xbe483f6d,0xbf7b3ec4,
0x3e483f35,0xbf7b3f35,0x3f7bbf35,0x3e483f35,0x3f55bf6d,0x3f0e3ec4,0xbf0ebec4,0x3f55bf6d,0xbf460000,0x3f22bf80,0xbf7f3f35,0xbdc9bf35,
0xbef13f7b,0xbf623e48,0x3e953f0e,0xbf753f55,0x3f75bec4,0xbe953f6d,0x3f62bf6d,0x3ef13ec4,0x3dc9bf55,0x3f7fbf0e,0xbf22be48,0x3f46bf7b,
0xbf353f80,0xbf350000,0xbf353f80,0xbf350000,0x3f350000,0xbf353f80,0x3f350000,0xbf353f80,0x3f35bf80,0x3f350000,0x3f35bf80,0x3f350000,
0xbf350000,0x3f35bf80,0xbf350000,0x3f35bf80,0x3f220000,0xbf463f80,0xbdc93f35,0xbf7f3f35,0x3f62bf7b,0x3ef13e48,0x3f75bf0e,0xbe953f55,
0xbe95bec4,0x3f75bf6d,0x3ef1bf6d,0x3f62bec4,0xbf7f3f55,0xbdc9bf0e,0xbf463e48,0x3f22bf7b,0x3f55bf80,0x3f0e0000,0x3f0e0000,0xbf553f80,
0xbe48bec4,0x3f7bbf6d,0x3f7bbf6d,0x3e483ec4,0xbf7b3f35,0x3e48bf35,0x3e48bf35,0x3f7bbf35,0xbf0e3f6d,0xbf553ec4,0xbf553ec4,0x3f0ebf6d,
0xbef10000,0x3f62bf80,0x3f75bf35,0xbe953f35,0xbf7f3f55,0x3dc9bf0e,0x3f46bf7b,0x3f22be48,0xbf223f6d,0xbf463ec4,0xbdc9bec4,0x3f7fbf6d,
0x3e953e48,0xbf753f7b,0xbf623f0e,0x3ef1bf55,0xbf6d3f80,0xbec40000,0x3f6dbf80,0x3ec40000,0xbec43f35,0xbf6d3f35,0x3ec4bf35,0x3f6dbf35,
0x3ec40000,0xbf6d3f80,0xbec40000,0x3f6dbf80,0x3f6dbf35,0xbec43f35,0xbf6d3f35,0x3ec4bf35,0x3e950000,0xbf753f80,0x3ef1bf35,0x3f62bf35,
0x3f46bf0e,0xbf223f55,0xbdc9be48,0x3f7fbf7b,0x3f7fbf6d,0xbdc93ec4,0xbf223ec4,0x3f46bf6d,0x3f62bf7b,0x3ef1be48,0xbf753f55,0x3e95bf0e,
0x3f7bbf80,0x3e480000,0xbe480000,0x3f7bbf80,0x3f55bf6d,0x3f0ebec4,0xbf0e3ec4,0x3f55bf6d,0x3f0ebf35,0x3f55bf35,0xbf553f35,0x3f0ebf35,
0x3e48bec4,0x3f7bbf6d,0xbf7b3f6d,0x3e48bec4,0xbdc90000,0x3f7fbf80,0xbf463f35,0x3f22bf35,0xbe953e48,0x3f75bf7b,0xbf623f55,0x3ef1bf0e,
0xbef13ec4,0x3f62bf6d,0xbf753f6d,0x3e95bec4,0xbf223f0e,0x3f46bf55,0xbf7f3f7b,0x3dc9be48,0x40003f80,0x3fb53f80,0x3f80,0xbfb53f80,
0x40004000,0xbfb50000,0x0,0xbfb5c000,0x40004000,0xbfb5c000,0x0,0x3fb50000,0x40004000,0x3fb50000,0x0,0x3fb54000,
0x3fff3f80,0x3fa23f80,0xbe49bf80,0xbfc6bf80,0x3ff53ffb,0xbfe2bec8,0xbf15bec8,0xbf71bffb,0x3fe23fed,0xbf15bfed,0xbf71bf44,0x3ff53f44,
0x3fc63fd5,0x3fff3f8e,0xbfa2bf8e,0x3e493fd5,0x3ffb3f80,0x3f8e3f80,0xbec83f80,0xbfd53f80,0x3fd53fed,0xbffbbf44,0xbf8ebf44,0xbec8bfed,
0x3f8e3fb5,0x3ec8bfb5,0xbfd5bfb5,0x3ffb3fb5,0x3ec83f44,0x3fd53fed,0xbffbbfed,0xbf8e3f44,0x3ff53f80,0x3f713f80,0xbf15bf80,0xbfe2bf80,
0x3fa23fd5,0xbfffbf8e,0xbfc6bf8e,0x3e49bfd5,0x3e493f44,0x3fa2bf44,0xbfffbfed,0x3fc63fed,0xbf71bec8,0x3f153ffb,0xbfe2bffb,0xbff5bec8,
0x3fed3f80,0x3f443f80,0xbf443f80,0xbfed3f80,0x3f443fb5,0xbfedbfb5,0xbfedbfb5,0x3f44bfb5,0xbf440000,0x3fed0000,0xbfedc000,0x3f444000,
0xbfedbfb5,0xbf443fb5,0xbf44bfb5,0xbfedbfb5,0x3fe23f80,0x3f153f80,0xbf71bf80,0xbff5bf80,0x3e493f8e,0xbfc6bfd5,0xbfffbfd5,0x3fa2bf8e,
0xbfc6bf44,0x3fff3f44,0xbfa2bfed,0xbe493fed,0xbff5bffb,0xbfe23ec8,0x3f15bec8,0xbf71bffb,0x3fd53f80,0x3ec83f80,0xbf8e3f80,0xbffb3f80,
0xbec83f44,0xbf8ebfed,0xbffbbfed,0x3fd5bf44,0xbffbbfb5,0x3fd53fb5,0xbec8bfb5,0xbf8e3fb5,0xbf8ebfed,0xbffbbf44,0x3fd53f44,0x3ec8bfed,
0x3fc63f80,0x3e493f80,0xbfa2bf80,0xbfffbf80,0xbf713ec8,0xbf15bffb,0xbfe2bffb,0x3ff5bec8,0xbff5bfed,0x3f713fed,0x3f15bf44,0xbfe23f44,
0x3e49bf8e,0xbfa2bfd5,0x3fff3fd5,0x3fc6bf8e,0x3f80,0xbfb53f80,0xc0003f80,0xbfb53f80,0xc000,0x3fb50000,0x40000000,0xbfb54000,
0x4000,0x3fb5c000,0xc0000000,0x3fb50000,0xc000,0xbfb50000,0x40000000,0x3fb5c000,0xbe493f80,0xbfc63f80,0xbfffbf80,0xbfa2bf80,
0x3f15bffb,0x3f713ec8,0x3ff53ec8,0xbfe23ffb,0xbf713fed,0x3ff5bfed,0xbfe2bf44,0x3f153f44,0x3fa2bfd5,0xbe49bf8e,0x3fc63f8e,0x3fffbfd5,
0xbec83f80,0xbfd53f80,0xbffb3f80,0xbf8e3f80,0x3f8ebfed,0x3ec83f44,0x3fd53f44,0xbffb3fed,0xbfd53fb5,0x3ffbbfb5,0xbf8ebfb5,0xbec83fb5,
0x3ffbbf44,0x3f8ebfed,0x3ec83fed,0x3fd5bf44,0xbf153f80,0xbfe23f80,0xbff5bf80,0xbf71bf80,0x3fc6bfd5,0xbe493f8e,0x3fa23f8e,0xbfff3fd5,
0xbfff3f44,0x3fc6bf44,0xbe49bfed,0xbfa23fed,0x3fe23ec8,0x3ff5bffb,0xbf713ffb,0x3f153ec8,0xbf443f80,0xbfed3f80,0xbfed3f80,0xbf443f80,
0x3fedbfb5,0xbf443fb5,0x3f443fb5,0xbfed3fb5,0xbfed0000,0x3f440000,0x3f44c000,0xbfed4000,0x3f443fb5,0x3fedbfb5,0xbfed3fb5,0xbf443fb5,
0xbf713f80,0xbff53f80,0xbfe2bf80,0xbf15bf80,0x3fffbf8e,0xbfa23fd5,0x3e493fd5,0xbfc63f8e,0xbfa2bf44,0xbe493f44,0x3fc6bfed,0xbfff3fed,
0xbf153ffb,0x3f71bec8,0xbff53ec8,0xbfe23ffb,0xbf8e3f80,0xbffb3f80,0xbfd53f80,0xbec83f80,0x3ffbbf44,0xbfd53fed,0xbec83fed,0xbf8e3f44,
0xbec8bfb5,0xbf8e3fb5,0x3ffbbfb5,0xbfd53fb5,0xbfd53fed,0xbec83f44,0xbf8ebf44,0xbffb3fed,0xbfa23f80,0xbfff3f80,0xbfc6bf80,0xbe49bf80,
0x3fe2bec8,0xbff53ffb,0xbf713ffb,0xbf153ec8,0x3f15bfed,0xbfe23fed,0x3ff5bf44,0xbf713f44,0xbfff3f8e,0xbfc63fd5,0x3e49bfd5,0xbfa23f8e,
0xc0003f80,0xbfb53f80,0x3f80,0x3fb53f80,0xc0004000,0x3fb50000,0x0,0x3fb5c000,0xc0004000,0x3fb5c000,0x0,0xbfb50000,
0xc0004000,0xbfb50000,0x0,0xbfb54000,0xbfff3f80,0xbfa23f80,0x3e49bf80,0x3fc6bf80,0xbff53ffb,0x3fe2bec8,0x3f15bec8,0x3f71bffb,
0xbfe23fed,0x3f15bfed,0x3f71bf44,0xbff53f44,0xbfc63fd5,0xbfff3f8e,0x3fa2bf8e,0xbe493fd5,0xbffb3f80,0xbf8e3f80,0x3ec83f80,0x3fd53f80,
0xbfd53fed,0x3ffbbf44,0x3f8ebf44,0x3ec8bfed,0xbf8e3fb5,0xbec8bfb5,0x3fd5bfb5,0xbffb3fb5,0xbec83f44,0xbfd53fed,0x3ffbbfed,0x3f8e3f44,
0xbff53f80,0xbf713f80,0x3f15bf80,0x3fe2bf80,0xbfa23fd5,0x3fffbf8e,0x3fc6bf8e,0xbe49bfd5,0xbe493f44,0xbfa2bf44,0x3fffbfed,0xbfc63fed,
0x3f71bec8,0xbf153ffb,0x3fe2bffb,0x3ff5bec8,0xbfed3f80,0xbf443f80,0x3f443f80,0x3fed3f80,0xbf443fb5,0x3fedbfb5,0x3fedbfb5,0xbf44bfb5,
0x3f440000,0xbfed0000,0x3fedc000,0xbf444000,0x3fedbfb5,0x3f443fb5,0x3f44bfb5,0x3fedbfb5,0xbfe23f80,0xbf153f80,0x3f71bf80,0x3ff5bf80,
0xbe493f8e,0x3fc6bfd5,0x3fffbfd5,0xbfa2bf8e,0x3fc6bf44,0xbfff3f44,0x3fa2bfed,0x3e493fed,0x3ff5bffb,0x3fe23ec8,0xbf15bec8,0x3f71bffb,
0xbfd53f80,0xbec83f80,0x3f8e3f80,0x3ffb3f80,0x3ec83f44,0x3f8ebfed,0x3ffbbfed,0xbfd5bf44,0x3ffbbfb5,0xbfd53fb5,0x3ec8bfb5,0x3f8e3fb5,
0x3f8ebfed,0x3ffbbf44,0xbfd53f44,0xbec8bfed,0xbfc63f80,0xbe493f80,0x3fa2bf80,0x3fffbf80,0x3f713ec8,0x3f15bffb,0x3fe2bffb,0xbff5bec8,
0x3ff5bfed,0xbf713fed,0xbf15bf44,0x3fe23f44,0xbe49bf8e,0x3fa2bfd5,0xbfff3fd5,0xbfc6bf8e,0x3f80,0x3fb53f80,0x40003f80,0x3fb53f80,
0xc000,0xbfb50000,0xc0000000,0x3fb54000,0x4000,0xbfb5c000,0x40000000,0xbfb50000,0xc000,0x3fb50000,0xc0000000,0xbfb5c000,
0x3e493f80,0x3fc63f80,0x3fffbf80,0x3fa2bf80,0xbf15bffb,0xbf713ec8,0xbff53ec8,0x3fe23ffb,0x3f713fed,0xbff5bfed,0x3fe2bf44,0xbf153f44,
0xbfa2bfd5,0x3e49bf8e,0xbfc63f8e,0xbfffbfd5,0x3ec83f80,0x3fd53f80,0x3ffb3f80,0x3f8e3f80,0xbf8ebfed,0xbec83f44,0xbfd53f44,0x3ffb3fed,
0x3fd53fb5,0xbffbbfb5,0x3f8ebfb5,0x3ec83fb5,0xbffbbf44,0xbf8ebfed,0xbec83fed,0xbfd5bf44,0x3f153f80,0x3fe23f80,0x3ff5bf80,0x3f71bf80,
0xbfc6bfd5,0x3e493f8e,0xbfa23f8e,0x3fff3fd5,0x3fff3f44,0xbfc6bf44,0x3e49bfed,0x3fa23fed,0xbfe23ec8,0xbff5bffb,0x3f713ffb,0xbf153ec8,
0x3f443f80,0x3fed3f80,0x3fed3f80,0x3f443f80,0xbfedbfb5,0x3f443fb5,0xbf443fb5,0x3fed3fb5,0x3fed0000,0xbf440000,0xbf44c000,0x3fed4000,
0xbf443fb5,0xbfedbfb5,0x3fed3fb5,0x3f443fb5,0x3f713f80,0x3ff53f80,0x3fe2bf80,0x3f15bf80,0xbfffbf8e,0x3fa23fd5,0xbe493fd5,0x3fc63f8e,
0x3fa2bf44,0x3e493f44,0xbfc6bfed,0x3fff3fed,0x3f153ffb,0xbf71bec8,0x3ff53ec8,0x3fe23ffb,0x3f8e3f80,0x3ffb3f80,0x3fd53f80,0x3ec83f80,
0xbffbbf44,0x3fd53fed,0x3ec83fed,0x3f8e3f44,0x3ec8bfb5,0x3f8e3fb5,0xbffbbfb5,0x3fd53fb5,0x3fd53fed,0x3ec83f44,0x3f8ebf44,0x3ffb3fed,
0x3fa23f80,0x3fff3f80,0x3fc6bf80,0x3e49bf80,0xbfe2bec8,0x3ff53ffb,0x3f713ffb,0x3f153ec8,0xbf15bfed,0x3fe23fed,0xbff5bf44,0x3f713f44,
0x3fff3f8e,0x3fc63fd5,0xbe49bfd5,0x3fa23f8e,0x40004000,0x3fb54000,0x0,0xbfb50000,0x40004000,0xbfb50000,0x0,0xbfb5c000,
0x40004000,0xbfb5c000,0x0,0x3fb50000,0x40004000,0x3fb50000,0x0,0x3fb54000,0x3fa23fb5,0xbe493fb5,0xbfc6bfb5,0xbfffbfb5,
0x3f713f8e,0xbff5bfd5,0xbfe2bfd5,0x3f15bf8e,0x3f153f44,0x3f71bf44,0xbff5bfed,0x3fe23fed,0x3e493ec8,0x3fc63ffb,0xbfffbffb,0xbfa23ec8,
0xbec80000,0xbfd50000,0xbffbc000,0xbf8ec000,0xbf8ebf44,0xbec8bfed,0xbfd5bfed,0x3ffb3f44,0xbfd5bfb5,0x3ffb3fb5,0xbf8ebfb5,0xbec83fb5,
0xbffbbfed,0xbf8e3f44,0xbec8bf44,0xbfd5bfed,0xbfe2bfb5,0xbff5bfb5,0xbf71bfb5,0x3f15bfb5,0xbfffbffb,0x3fc6bec8,0x3e49bec8,0x3fa23ffb,
0xbfc6bfed,0x3e493fed,0x3fa23f44,0xbfffbf44,0xbf15bf8e,0xbfe2bfd5,0x3ff53fd5,0x3f71bf8e,0xbfedc000,0xbf44c000,0x3f440000,0x3fed0000,
0xbf44bfb5,0x3fed3fb5,0x3fed3fb5,0xbf443fb5,0x3f440000,0xbfed0000,0x3fed4000,0xbf44c000,0x3fed3fb5,0x3f44bfb5,0x3f443fb5,0x3fed3fb5,
0xbf15bfb5,0x3f71bfb5,0x3ff53fb5,0x3fe23fb5,0x3fa23ec8,0x3e493ffb,0x3fc63ffb,0xbfffbec8,0x3fff3fed,0xbfa2bfed,0xbe493f44,0x3fc6bf44,
0x3f713fd5,0x3ff53f8e,0xbfe2bf8e,0xbf153fd5,0x3f8e0000,0x3ffb0000,0x3fd54000,0x3ec84000,0x3ffb3fed,0xbfd53f44,0xbec83f44,0xbf8ebfed,
0x3ec83fb5,0x3f8ebfb5,0xbffbbfb5,0x3fd53fb5,0xbfd5bf44,0xbec83fed,0xbf8ebfed,0xbffbbf44,0x3fff3fb5,0x3fc63fb5,0x3e493fb5,0xbfa23fb5,
0x3f153fd5,0xbfe2bf8e,0xbff5bf8e,0x3f71bfd5,0xbfe2bf44,0x3ff53f44,0xbf71bfed,0xbf153fed,0xbfa2bffb,0xbfffbec8,0x3fc63ec8,0x3e49bffb,
0x4000,0xbfb54000,0xc0000000,0xbfb50000,0xc000,0x3fb50000,0x40000000,0xbfb54000,0x4000,0x3fb5c000,0xc0000000,0x3fb50000,
0xc000,0xbfb50000,0x40000000,0x3fb5c000,0xbfc63fb5,0xbfff3fb5,0xbfa2bfb5,0x3e49bfb5,0x3fe2bf8e,0xbf153fd5,0x3f713fd5,0xbff53f8e,
0xbff53f44,0x3fe2bf44,0xbf15bfed,0xbf713fed,0x3fffbec8,0x3fa2bffb,0x3e493ffb,0x3fc6bec8,0xbffb0000,0xbf8e0000,0x3ec8c000,0x3fd5c000,
0x3fd53f44,0xbffb3fed,0xbf8e3fed,0xbec8bf44,0xbf8ebfb5,0xbec83fb5,0x3fd5bfb5,0xbffb3fb5,0x3ec83fed,0x3fd5bf44,0xbffb3f44,0xbf8e3fed,
0xbf71bfb5,0x3f15bfb5,0x3fe2bfb5,0x3ff5bfb5,0xbe493ffb,0xbfa23ec8,0xbfff3ec8,0x3fc6bffb,0x3fa2bfed,0xbfff3fed,0x3fc63f44,0xbe49bf44,
0xbff53f8e,0xbf713fd5,0xbf15bfd5,0xbfe23f8e,0x3f44c000,0x3fedc000,0x3fed0000,0x3f440000,0xbfed3fb5,0x3f44bfb5,0xbf44bfb5,0x3fedbfb5,
0x3fed0000,0xbf440000,0xbf444000,0x3fedc000,0xbf44bfb5,0xbfed3fb5,0x3fedbfb5,0x3f44bfb5,0x3ff5bfb5,0x3fe2bfb5,0x3f153fb5,0xbf713fb5,
0xbfc6bec8,0x3fffbffb,0x3fa2bffb,0x3e493ec8,0xbe493fed,0x3fc6bfed,0xbfff3f44,0x3fa2bf44,0x3fe2bfd5,0x3f15bf8e,0x3f713f8e,0x3ff5bfd5,
0x3fd50000,0x3ec80000,0xbf8e4000,0xbffb4000,0x3ec8bfed,0x3f8ebf44,0x3ffbbf44,0xbfd53fed,0xbffb3fb5,0x3fd5bfb5,0xbec8bfb5,0xbf8e3fb5,
0x3f8e3f44,0x3ffbbfed,0xbfd53fed,0xbec83f44,0x3e493fb5,0xbfa23fb5,0xbfff3fb5,0xbfc63fb5,0x3ff5bfd5,0xbf713f8e,0x3f153f8e,0xbfe23fd5,
0xbf71bf44,0xbf153f44,0x3fe2bfed,0xbff53fed,0xbfc63ffb,0xbe493ec8,0xbfa2bec8,0xbfff3ffb,0xc0004000,0xbfb54000,0x0,0x3fb50000,
0xc0004000,0x3fb50000,0x0,0x3fb5c000,0xc0004000,0x3fb5c000,0x0,0xbfb50000,0xc0004000,0xbfb50000,0x0,0xbfb54000,
0xbfa23fb5,0x3e493fb5,0x3fc6bfb5,0x3fffbfb5,0xbf713f8e,0x3ff5bfd5,0x3fe2bfd5,0xbf15bf8e,0xbf153f44,0xbf71bf44,0x3ff5bfed,0xbfe23fed,
0xbe493ec8,0xbfc63ffb,0x3fffbffb,0x3fa23ec8,0x3ec80000,0x3fd50000,0x3ffbc000,0x3f8ec000,0x3f8ebf44,0x3ec8bfed,0x3fd5bfed,0xbffb3f44,
0x3fd5bfb5,0xbffb3fb5,0x3f8ebfb5,0x3ec83fb5,0x3ffbbfed,0x3f8e3f44,0x3ec8bf44,0x3fd5bfed,0x3fe2bfb5,0x3ff5bfb5,0x3f71bfb5,0xbf15bfb5,
0x3fffbffb,0xbfc6bec8,0xbe49bec8,0xbfa23ffb,0x3fc6bfed,0xbe493fed,0xbfa23f44,0x3fffbf44,0x3f15bf8e,0x3fe2bfd5,0xbff53fd5,0xbf71bf8e,
0x3fedc000,0x3f44c000,0xbf440000,0xbfed0000,0x3f44bfb5,0xbfed3fb5,0xbfed3fb5,0x3f443fb5,0xbf440000,0x3fed0000,0xbfed4000,0x3f44c000,
0xbfed3fb5,0xbf44bfb5,0xbf443fb5,0xbfed3fb5,0x3f15bfb5,0xbf71bfb5,0xbff53fb5,0xbfe23fb5,0xbfa23ec8,0xbe493ffb,0xbfc63ffb,0x3fffbec8,
0xbfff3fed,0x3fa2bfed,0x3e493f44,0xbfc6bf44,0xbf713fd5,0xbff53f8e,0x3fe2bf8e,0x3f153fd5,0xbf8e0000,0xbffb0000,0xbfd54000,0xbec84000,
0xbffb3fed,0x3fd53f44,0x3ec83f44,0x3f8ebfed,0xbec83fb5,0xbf8ebfb5,0x3ffbbfb5,0xbfd53fb5,0x3fd5bf44,0x3ec83fed,0x3f8ebfed,0x3ffbbf44,
0xbfff3fb5,0xbfc63fb5,0xbe493fb5,0x3fa23fb5,0xbf153fd5,0x3fe2bf8e,0x3ff5bf8e,0xbf71bfd5,0x3fe2bf44,0xbff53f44,0x3f71bfed,0x3f153fed,
0x3fa2bffb,0x3fffbec8,0xbfc63ec8,0xbe49bffb,0x4000,0x3fb54000,0x40000000,0x3fb50000,0xc000,0xbfb50000,0xc0000000,0x3fb54000,
0x4000,0xbfb5c000,0x40000000,0xbfb50000,0xc000,0x3fb50000,0xc0000000,0xbfb5c000,0x3fc63fb5,0x3fff3fb5,0x3fa2bfb5,0xbe49bfb5,
0xbfe2bf8e,0x3f153fd5,0xbf713fd5,0x3ff53f8e,0x3ff53f44,0xbfe2bf44,0x3f15bfed,0x3f713fed,0xbfffbec8,0xbfa2bffb,0xbe493ffb,0xbfc6bec8,
0x3ffb0000,0x3f8e0000,0xbec8c000,0xbfd5c000,0xbfd53f44,0x3ffb3fed,0x3f8e3fed,0x3ec8bf44,0x3f8ebfb5,0x3ec83fb5,0xbfd5bfb5,0x3ffb3fb5,
0xbec83fed,0xbfd5bf44,0x3ffb3f44,0x3f8e3fed,0x3f71bfb5,0xbf15bfb5,0xbfe2bfb5,0xbff5bfb5,0x3e493ffb,0x3fa23ec8,0x3fff3ec8,0xbfc6bffb,
0xbfa2bfed,0x3fff3fed,0xbfc63f44,0x3e49bf44,0x3ff53f8e,0x3f713fd5,0x3f15bfd5,0x3fe23f8e,0xbf44c000,0xbfedc000,0xbfed0000,0xbf440000,
0x3fed3fb5,0xbf44bfb5,0x3f44bfb5,0xbfedbfb5,0xbfed0000,0x3f440000,0x3f444000,0xbfedc000,0x3f44bfb5,0x3fed3fb5,0xbfedbfb5,0xbf44bfb5,
0xbff5bfb5,0xbfe2bfb5,0xbf153fb5,0x3f713fb5,0x3fc6bec8,0xbfffbffb,0xbfa2bffb,0xbe493ec8,0x3e493fed,0xbfc6bfed,0x3fff3f44,0xbfa2bf44,
0xbfe2bfd5,0xbf15bf8e,0xbf713f8e,0xbff5bfd5,0xbfd50000,0xbec80000,0x3f8e4000,0x3ffb4000,0xbec8bfed,0xbf8ebf44,0xbffbbf44,0x3fd53fed,
0x3ffb3fb5,0xbfd5bfb5,0x3ec8bfb5,0x3f8e3fb5,0xbf8e3f44,0xbffbbfed,0x3fd53fed,0x3ec83f44,0xbe493fb5,0x3fa23fb5,0x3fff3fb5,0x3fc63fb5,
0xbff5bfd5,0x3f713f8e,0xbf153f8e,0x3fe23fd5,0x3f71bf44,0x3f153f44,0xbfe2bfed,0x3ff53fed,0x3fc63ffb,0x3e493ec8,0x3fa2bec8,0x3fff3ffb,
0x40004000,0x3fb54000,0x0,0xbfb50000,0x40004000,0xbfb50000,0x0,0xbfb5c000,0x40004000,0xbfb5c000,0x0,0x3fb50000,
0x40004000,0x3fb50000,0x0,0x3fb54000,0xbe490000,0xbfc60000,0xbfffc000,0xbfa2c000,0xbf15bec8,0xbf71bffb,0xbff5bffb,0x3fe23ec8,
0xbf71bf44,0x3ff53f44,0xbfe2bfed,0x3f153fed,0xbfa2bf8e,0x3e493fd5,0xbfc6bfd5,0xbfffbf8e,0xbffbc000,0xbf8ec000,0x3ec80000,0x3fd50000,
0xbfd5bfed,0x3ffb3f44,0x3f8e3f44,0x3ec83fed,0xbf8ebfb5,0xbec83fb5,0x3fd53fb5,0xbffbbfb5,0xbec8bf44,0xbfd5bfed,0x3ffb3fed,0x3f8ebf44,
0x3f150000,0x3fe20000,0x3ff54000,0x3f714000,0x3fc63f8e,0xbe493fd5,0x3fa23fd5,0xbfffbf8e,0x3fff3fed,0xbfc6bfed,0x3e493f44,0x3fa2bf44,
0x3fe23ffb,0x3ff53ec8,0xbf71bec8,0x3f153ffb,0x3fed4000,0x3f444000,0xbf440000,0xbfed0000,0x3f443fb5,0xbfedbfb5,0xbfedbfb5,0x3f44bfb5,
0xbf440000,0x3fed0000,0xbfedc000,0x3f444000,0xbfedbfb5,0xbf443fb5,0xbf44bfb5,0xbfedbfb5,0xbf710000,0xbff50000,0xbfe2c000,0xbf15c000,
0xbfffbfd5,0x3fa2bf8e,0xbe49bf8e,0x3fc63fd5,0xbfa2bfed,0xbe493fed,0x3fc63f44,0xbfffbf44,0x3f15bec8,0xbf71bffb,0x3ff53ffb,0x3fe2bec8,
0xbfd5c000,0xbec8c000,0x3f8e0000,0x3ffb0000,0x3ec8bf44,0x3f8e3fed,0x3ffb3fed,0xbfd53f44,0x3ffb3fb5,0xbfd5bfb5,0x3ec83fb5,0x3f8ebfb5,
0x3f8e3fed,0x3ffb3f44,0xbfd5bf44,0xbec83fed,0x3fa20000,0x3fff0000,0x3fc64000,0x3e494000,0x3fe23ffb,0xbff53ec8,0xbf713ec8,0xbf15bffb,
0xbf153f44,0x3fe2bf44,0xbff5bfed,0x3f713fed,0xbfffbfd5,0xbfc63f8e,0x3e49bf8e,0xbfa2bfd5,0x4000,0xbfb54000,0xc0000000,0xbfb50000,
0xc000,0x3fb50000,0x40000000,0xbfb54000,0x4000,0x3fb5c000,0xc0000000,0x3fb50000,0xc000,0xbfb50000,0x40000000,0x3fb5c000,
0xbfff0000,0xbfa20000,0x3e49c000,0x3fc6c000,0x3ff53ec8,0xbfe23ffb,0xbf153ffb,0xbf71bec8,0xbfe2bf44,0x3f153f44,0x3f71bfed,0xbff53fed,
0x3fc63f8e,0x3fffbfd5,0xbfa23fd5,0x3e493f8e,0x3ec8c000,0x3fd5c000,0x3ffb0000,0x3f8e0000,0xbf8e3fed,0xbec8bf44,0xbfd5bf44,0x3ffbbfed,
0x3fd5bfb5,0xbffb3fb5,0x3f8e3fb5,0x3ec8bfb5,0xbffb3f44,0xbf8e3fed,0xbec8bfed,0xbfd53f44,0x3ff50000,0x3f710000,0xbf154000,0xbfe24000,
0xbfa2bf8e,0x3fffbfd5,0x3fc6bfd5,0xbe493f8e,0x3e493fed,0x3fa2bfed,0xbfff3f44,0x3fc6bf44,0x3f71bffb,0xbf15bec8,0x3fe23ec8,0x3ff5bffb,
0xbf444000,0xbfed4000,0xbfed0000,0xbf440000,0x3fedbfb5,0xbf443fb5,0x3f443fb5,0xbfed3fb5,0xbfed0000,0x3f440000,0x3f44c000,0xbfed4000,
0x3f443fb5,0x3fedbfb5,0xbfed3fb5,0xbf443fb5,0xbfe20000,0xbf150000,0x3f71c000,0x3ff5c000,0x3e493fd5,0xbfc63f8e,0xbfff3f8e,0x3fa2bfd5,
0x3fc6bfed,0xbfff3fed,0x3fa23f44,0x3e49bf44,0xbff53ec8,0xbfe23ffb,0x3f15bffb,0xbf713ec8,0x3f8ec000,0x3ffbc000,0x3fd50000,0x3ec80000,
0xbffb3f44,0x3fd5bfed,0x3ec8bfed,0x3f8ebf44,0x3ec83fb5,0x3f8ebfb5,0xbffb3fb5,0x3fd5bfb5,0x3fd5bfed,0x3ec8bf44,0x3f8e3f44,0x3ffbbfed,
0x3fc60000,0x3e490000,0xbfa24000,0xbfff4000,0x3f71bffb,0x3f15bec8,0x3fe2bec8,0xbff53ffb,0xbff53f44,0x3f71bf44,0x3f15bfed,0xbfe23fed,
0xbe493fd5,0x3fa2bf8e,0xbfff3f8e,0xbfc63fd5,0xc0004000,0xbfb54000,0x0,0x3fb50000,0xc0004000,0x3fb50000,0x0,0x3fb5c000,
0xc0004000,0x3fb5c000,0x0,0xbfb50000,0xc0004000,0xbfb50000,0x0,0xbfb54000,0x3e490000,0x3fc60000,0x3fffc000,0x3fa2c000,
0x3f15bec8,0x3f71bffb,0x3ff5bffb,0xbfe23ec8,0x3f71bf44,0xbff53f44,0x3fe2bfed,0xbf153fed,0x3fa2bf8e,0xbe493fd5,0x3fc6bfd5,0x3fffbf8e,
0x3ffbc000,0x3f8ec000,0xbec80000,0xbfd50000,0x3fd5bfed,0xbffb3f44,0xbf8e3f44,0xbec83fed,0x3f8ebfb5,0x3ec83fb5,0xbfd53fb5,0x3ffbbfb5,
0x3ec8bf44,0x3fd5bfed,0xbffb3fed,0xbf8ebf44,0xbf150000,0xbfe20000,0xbff54000,0xbf714000,0xbfc63f8e,0x3e493fd5,0xbfa23fd5,0x3fffbf8e,
0xbfff3fed,0x3fc6bfed,0xbe493f44,0xbfa2bf44,0xbfe23ffb,0xbff53ec8,0x3f71bec8,0xbf153ffb,0xbfed4000,0xbf444000,0x3f440000,0x3fed0000,
0xbf443fb5,0x3fedbfb5,0x3fedbfb5,0xbf44bfb5,0x3f440000,0xbfed0000,0x3fedc000,0xbf444000,0x3fedbfb5,0x3f443fb5,0x3f44bfb5,0x3fedbfb5,
0x3f710000,0x3ff50000,0x3fe2c000,0x3f15c000,0x3fffbfd5,0xbfa2bf8e,0x3e49bf8e,0xbfc63fd5,0x3fa2bfed,0x3e493fed,0xbfc63f44,0x3fffbf44,
0xbf15bec8,0x3f71bffb,0xbff53ffb,0xbfe2bec8,0x3fd5c000,0x3ec8c000,0xbf8e0000,0xbffb0000,0xbec8bf44,0xbf8e3fed,0xbffb3fed,0x3fd53f44,
0xbffb3fb5,0x3fd5bfb5,0xbec83fb5,0xbf8ebfb5,0xbf8e3fed,0xbffb3f44,0x3fd5bf44,0x3ec83fed,0xbfa20000,0xbfff0000,0xbfc64000,0xbe494000,
0xbfe23ffb,0x3ff53ec8,0x3f713ec8,0x3f15bffb,0x3f153f44,0xbfe2bf44,0x3ff5bfed,0xbf713fed,0x3fffbfd5,0x3fc63f8e,0xbe49bf8e,0x3fa2bfd5,
0x4000,0x3fb54000,0x40000000,0x3fb50000,0xc000,0xbfb50000,0xc0000000,0x3fb54000,0x4000,0xbfb5c000,0x40000000,0xbfb50000,
0xc000,0x3fb50000,0xc0000000,0xbfb5c000,0x3fff0000,0x3fa20000,0xbe49c000,0xbfc6c000,0xbff53ec8,0x3fe23ffb,0x3f153ffb,0x3f71bec8,
0x3fe2bf44,0xbf153f44,0xbf71bfed,0x3ff53fed,0xbfc63f8e,0xbfffbfd5,0x3fa23fd5,0xbe493f8e,0xbec8c000,0xbfd5c000,0xbffb0000,0xbf8e0000,
0x3f8e3fed,0x3ec8bf44,0x3fd5bf44,0xbffbbfed,0xbfd5bfb5,0x3ffb3fb5,0xbf8e3fb5,0xbec8bfb5,0x3ffb3f44,0x3f8e3fed,0x3ec8bfed,0x3fd53f44,
0xbff50000,0xbf710000,0x3f154000,0x3fe24000,0x3fa2bf8e,0xbfffbfd5,0xbfc6bfd5,0x3e493f8e,0xbe493fed,0xbfa2bfed,0x3fff3f44,0xbfc6bf44,
0xbf71bffb,0x3f15bec8,0xbfe23ec8,0xbff5bffb,0x3f444000,0x3fed4000,0x3fed0000,0x3f440000,0xbfedbfb5,0x3f443fb5,0xbf443fb5,0x3fed3fb5,
0x3fed0000,0xbf440000,0xbf44c000,0x3fed4000,0xbf443fb5,0xbfedbfb5,0x3fed3fb5,0x3f443fb5,0x3fe20000,0x3f150000,0xbf71c000,0xbff5c000,
0xbe493fd5,0x3fc63f8e,0x3fff3f8e,0xbfa2bfd5,0xbfc6bfed,0x3fff3fed,0xbfa23f44,0xbe49bf44,0x3ff53ec8,0x3fe23ffb,0xbf15bffb,0x3f713ec8,
0xbf8ec000,0xbffbc000,0xbfd50000,0xbec80000,0x3ffb3f44,0xbfd5bfed,0xbec8bfed,0xbf8ebf44,0xbec83fb5,0xbf8ebfb5,0x3ffb3fb5,0xbfd5bfb5,
0xbfd5bfed,0xbec8bf44,0xbf8e3f44,0xbffbbfed,0xbfc60000,0xbe490000,0x3fa24000,0x3fff4000,0xbf71bffb,0xbf15bec8,0xbfe2bec8,0x3ff53ffb,
0x3ff53f44,0xbf71bf44,0xbf15bfed,0x3fe23fed,0x3e493fd5,0xbfa2bf8e,0x3fff3f8e,0x3fc63fd5,0x40004000,0x3fb54000,0x0,0xbfb50000,
0x40004000,0xbfb50000,0x0,0xbfb5c000,0x40004000,0xbfb5c000,0x0,0x3fb50000,0x40004000,0x3fb50000,0x0,0x3fb54000,
0xbfc6bfb5,0xbfffbfb5,0xbfa2bfb5,0x3e49bfb5,0xbfe2bfd5,0x3f15bf8e,0xbf71bf8e,0x3ff53fd5,0xbff5bfed,0x3fe23fed,0xbf15bf44,0xbf713f44,
0xbfffbffb,0xbfa23ec8,0xbe49bec8,0xbfc6bffb,0x3ec80000,0x3fd50000,0x3ffb4000,0x3f8e4000,0x3f8e3f44,0x3ec83fed,0x3fd53fed,0xbffbbf44,
0x3fd53fb5,0xbffbbfb5,0x3f8e3fb5,0x3ec8bfb5,0x3ffb3fed,0x3f8ebf44,0x3ec83f44,0x3fd53fed,0x3f713fb5,0xbf153fb5,0xbfe2bfb5,0xbff5bfb5,
0xbe493ec8,0xbfa2bffb,0xbfffbffb,0x3fc6bec8,0xbfa2bf44,0x3fff3f44,0xbfc6bfed,0x3e493fed,0xbff5bfd5,0xbf713f8e,0xbf15bf8e,0xbfe2bfd5,
0xbfedc000,0xbf44c000,0x3f440000,0x3fed0000,0xbf44bfb5,0x3fed3fb5,0x3fed3fb5,0xbf443fb5,0x3f440000,0xbfed0000,0x3fed4000,0xbf44c000,
0x3fed3fb5,0x3f44bfb5,0x3f443fb5,0x3fed3fb5,0x3ff53fb5,0x3fe23fb5,0x3f153fb5,0xbf713fb5,0x3fc63ffb,0xbfffbec8,0xbfa2bec8,0xbe49bffb,
0xbe493f44,0x3fc6bf44,0xbfffbfed,0x3fa23fed,0xbfe2bf8e,0xbf153fd5,0xbf71bfd5,0xbff5bf8e,0xbf8e0000,0xbffb0000,0xbfd5c000,0xbec8c000,
0xbffbbfed,0x3fd5bf44,0x3ec8bf44,0x3f8e3fed,0xbec8bfb5,0xbf8e3fb5,0x3ffb3fb5,0xbfd5bfb5,0x3fd53f44,0x3ec8bfed,0x3f8e3fed,0x3ffb3f44,
0xbe49bfb5,0x3fa2bfb5,0x3fff3fb5,0x3fc63fb5,0x3ff53f8e,0xbf713fd5,0x3f153fd5,0xbfe2bf8e,0x3f713fed,0x3f15bfed,0xbfe2bf44,0x3ff53f44,
0xbfc6bec8,0xbe493ffb,0xbfa2bffb,0xbfffbec8,0x4000,0xbfb54000,0xc0000000,0xbfb50000,0xc000,0x3fb50000,0x40000000,0xbfb54000,
0x4000,0x3fb5c000,0xc0000000,0x3fb50000,0xc000,0xbfb50000,0x40000000,0x3fb5c000,0xbfa2bfb5,0x3e49bfb5,0x3fc6bfb5,0x3fffbfb5,
0x3f713fd5,0xbff53f8e,0xbfe23f8e,0x3f15bfd5,0xbf15bfed,0xbf713fed,0x3ff5bf44,0xbfe23f44,0x3e493ffb,0x3fc6bec8,0xbfff3ec8,0xbfa23ffb,
0x3ffb0000,0x3f8e0000,0xbec84000,0xbfd54000,0xbfd5bf44,0x3ffbbfed,0x3f8ebfed,0x3ec83f44,0x3f8e3fb5,0x3ec8bfb5,0xbfd53fb5,0x3ffbbfb5,
0xbec8bfed,0xbfd53f44,0x3ffbbf44,0x3f8ebfed,0xbfe23fb5,0xbff53fb5,0xbf71bfb5,0x3f15bfb5,0x3fffbec8,0xbfc63ffb,0xbe493ffb,0xbfa23ec8,
0xbfc6bf44,0x3e493f44,0x3fa2bfed,0xbfff3fed,0x3f153fd5,0x3fe2bf8e,0xbff53f8e,0xbf713fd5,0x3f44c000,0x3fedc000,0x3fed0000,0x3f440000,
0xbfed3fb5,0x3f44bfb5,0xbf44bfb5,0x3fedbfb5,0x3fed0000,0xbf440000,0xbf444000,0x3fedc000,0xbf44bfb5,0xbfed3fb5,0x3fedbfb5,0x3f44bfb5,
0x3f153fb5,0xbf713fb5,0xbff53fb5,0xbfe23fb5,0x3fa2bffb,0x3e493ec8,0x3fc63ec8,0xbfff3ffb,0xbfff3f44,0x3fa2bf44,0x3e49bfed,0xbfc63fed,
0x3f713f8e,0x3ff5bfd5,0xbfe23fd5,0xbf153f8e,0xbfd50000,0xbec80000,0x3f8ec000,0x3ffbc000,0xbec83fed,0xbf8e3f44,0xbffb3f44,0x3fd5bfed,
0x3ffbbfb5,0xbfd53fb5,0x3ec83fb5,0x3f8ebfb5,0xbf8ebf44,0xbffb3fed,0x3fd5bfed,0x3ec8bf44,0x3fffbfb5,0x3fc6bfb5,0x3e493fb5,0xbfa23fb5,
0xbf15bf8e,0x3fe2bfd5,0x3ff5bfd5,0xbf713f8e,0xbfe23fed,0x3ff5bfed,0xbf71bf44,0xbf153f44,0x3fa23ec8,0x3fffbffb,0xbfc63ffb,0xbe493ec8,
0xc0004000,0xbfb54000,0x0,0x3fb50000,0xc0004000,0x3fb50000,0x0,0x3fb5c000,0xc0004000,0x3fb5c000,0x0,0xbfb50000,
0xc0004000,0xbfb50000,0x0,0xbfb54000,0x3fc6bfb5,0x3fffbfb5,0x3fa2bfb5,0xbe49bfb5,0x3fe2bfd5,0xbf15bf8e,0x3f71bf8e,0xbff53fd5,
0x3ff5bfed,0xbfe23fed,0x3f15bf44,0x3f713f44,0x3fffbffb,0x3fa23ec8,0x3e49bec8,0x3fc6bffb,0xbec80000,0xbfd50000,0xbffb4000,0xbf8e4000,
0xbf8e3f44,0xbec83fed,0xbfd53fed,0x3ffbbf44,0xbfd53fb5,0x3ffbbfb5,0xbf8e3fb5,0xbec8bfb5,0xbffb3fed,0xbf8ebf44,0xbec83f44,0xbfd53fed,
0xbf713fb5,0x3f153fb5,0x3fe2bfb5,0x3ff5bfb5,0x3e493ec8,0x3fa2bffb,0x3fffbffb,0xbfc6bec8,0x3fa2bf44,0xbfff3f44,0x3fc6bfed,0xbe493fed,
0x3ff5bfd5,0x3f713f8e,0x3f15bf8e,0x3fe2bfd5,0x3fedc000,0x3f44c000,0xbf440000,0xbfed0000,0x3f44bfb5,0xbfed3fb5,0xbfed3fb5,0x3f443fb5,
0xbf440000,0x3fed0000,0xbfed4000,0x3f44c000,0xbfed3fb5,0xbf44bfb5,0xbf443fb5,0xbfed3fb5,0xbff53fb5,0xbfe23fb5,0xbf153fb5,0x3f713fb5,
0xbfc63ffb,0x3fffbec8,0x3fa2bec8,0x3e49bffb,0x3e493f44,0xbfc6bf44,0x3fffbfed,0xbfa23fed,0x3fe2bf8e,0x3f153fd5,0x3f71bfd5,0x3ff5bf8e,
0x3f8e0000,0x3ffb0000,0x3fd5c000,0x3ec8c000,0x3ffbbfed,0xbfd5bf44,0xbec8bf44,0xbf8e3fed,0x3ec8bfb5,0x3f8e3fb5,0xbffb3fb5,0x3fd5bfb5,
0xbfd53f44,0xbec8bfed,0xbf8e3fed,0xbffb3f44,0x3e49bfb5,0xbfa2bfb5,0xbfff3fb5,0xbfc63fb5,0xbff53f8e,0x3f713fd5,0xbf153fd5,0x3fe2bf8e,
0xbf713fed,0xbf15bfed,0x3fe2bf44,0xbff53f44,0x3fc6bec8,0x3e493ffb,0x3fa2bffb,0x3fffbec8,0x4000,0x3fb54000,0x40000000,0x3fb50000,
0xc000,0xbfb50000,0xc0000000,0x3fb54000,0x4000,0xbfb5c000,0x40000000,0xbfb50000,0xc000,0x3fb50000,0xc0000000,0xbfb5c000,
0x3fa2bfb5,0xbe49bfb5,0xbfc6bfb5,0xbfffbfb5,0xbf713fd5,0x3ff53f8e,0x3fe23f8e,0xbf15bfd5,0x3f15bfed,0x3f713fed,0xbff5bf44,0x3fe23f44,
0xbe493ffb,0xbfc6bec8,0x3fff3ec8,0x3fa23ffb,0xbffb0000,0xbf8e0000,0x3ec84000,0x3fd54000,0x3fd5bf44,0xbffbbfed,0xbf8ebfed,0xbec83f44,
0xbf8e3fb5,0xbec8bfb5,0x3fd53fb5,0xbffbbfb5,0x3ec8bfed,0x3fd53f44,0xbffbbf44,0xbf8ebfed,0x3fe23fb5,0x3ff53fb5,0x3f71bfb5,0xbf15bfb5,
0xbfffbec8,0x3fc63ffb,0x3e493ffb,0x3fa23ec8,0x3fc6bf44,0xbe493f44,0xbfa2bfed,0x3fff3fed,0xbf153fd5,0xbfe2bf8e,0x3ff53f8e,0x3f713fd5,
0xbf44c000,0xbfedc000,0xbfed0000,0xbf440000,0x3fed3fb5,0xbf44bfb5,0x3f44bfb5,0xbfedbfb5,0xbfed0000,0x3f440000,0x3f444000,0xbfedc000,
0x3f44bfb5,0x3fed3fb5,0xbfedbfb5,0xbf44bfb5,0xbf153fb5,0x3f713fb5,0x3ff53fb5,0x3fe23fb5,0xbfa2bffb,0xbe493ec8,0xbfc63ec8,0x3fff3ffb,
0x3fff3f44,0xbfa2bf44,0xbe49bfed,0x3fc63fed,0xbf713f8e,0xbff5bfd5,0x3fe23fd5,0x3f153f8e,0x3fd50000,0x3ec80000,0xbf8ec000,0xbffbc000,
0x3ec83fed,0x3f8e3f44,0x3ffb3f44,0xbfd5bfed,0xbffbbfb5,0x3fd53fb5,0xbec83fb5,0xbf8ebfb5,0x3f8ebf44,0x3ffb3fed,0xbfd5bfed,0xbec8bf44,
0xbfffbfb5,0xbfc6bfb5,0xbe493fb5,0x3fa23fb5,0x3f15bf8e,0xbfe2bfd5,0xbff5bfd5,0x3f713f8e,0x3fe23fed,0xbff5bfed,0x3f71bf44,0x3f153f44,
0xbfa23ec8,0xbfffbffb,0x3fc63ffb,0x3e493ec8,0x80003f80,0x3f800000,0x80003f80,0x3f800000,0x80003f80,0x3f800000,0x80003f80,0x3f800000,
0x80003f80,0x3f800000,0x80003f80,0x3f800000,0x80003f80,0x3f800000,0x80003f80,0x3f800000,0x80003f80,0x3f800000,0x8000bf80,0xbf800000,
0x3f353f35,0x3f35bf35,0xbf35bf35,0xbf353f35,0x3f800000,0xbf80,0xbf800000,0x3f80,0x3f35bf35,0xbf35bf35,0xbf353f35,0x3f353f35,
0x80003f80,0x3f800000,0x80003f80,0x3f800000,0x3f800000,0xbf80,0x3f800000,0xbf80,0x8000bf80,0xbf800000,0x8000bf80,0xbf800000,
0xbf800000,0x3f80,0xbf800000,0x3f80,0x80003f80,0x3f800000,0x8000bf80,0xbf800000,0x3f35bf35,0xbf35bf35,0xbf353f35,0x3f353f35,
0xbf800000,0x3f80,0x3f800000,0xbf80,0x3f353f35,0x3f35bf35,0xbf35bf35,0xbf353f35,0x80003f80,0x3f800000,0x80003f80,0x3f800000,
0x8000bf80,0xbf800000,0x8000bf80,0xbf800000,0x80003f80,0x3f800000,0x80003f80,0x3f800000,0x8000bf80,0xbf800000,0x8000bf80,0xbf800000,
0x80003f80,0x3f800000,0x8000bf80,0xbf800000,0xbf35bf35,0xbf353f35,0x3f353f35,0x3f35bf35,0x3f800000,0xbf80,0xbf800000,0x3f80,
0xbf353f35,0x3f353f35,0x3f35bf35,0xbf35bf35,0x80003f80,0x3f800000,0x80003f80,0x3f800000,0xbf800000,0x3f80,0xbf800000,0x3f80,
0x8000bf80,0xbf800000,0x8000bf80,0xbf800000,0x3f800000,0xbf80,0x3f800000,0xbf80,0x80003f80,0x3f800000,0x8000bf80,0xbf800000,
0xbf353f35,0x3f353f35,0x3f35bf35,0xbf35bf35,0xbf800000,0x3f80,0x3f800000,0xbf80,0xbf35bf35,0xbf353f35,0x3f353f35,0x3f35bf35,
0x3f803f80,0x80008000,0x80008000,0xbf80bf80,0x3f803f80,0x80008000,0x80008000,0xbf80bf80,0x3f803f80,0x80008000,0x80008000,0xbf80bf80,
0x3f803f80,0x80008000,0x80008000,0xbf80bf80,0x3f353f80,0x3f358000,0x3f358000,0xbf35bf80,0xbf350000,0x3f353f80,0x3f353f80,0x3f358000,
0xbf35bf80,0xbf358000,0xbf358000,0x3f353f80,0x3f350000,0xbf35bf80,0xbf35bf80,0xbf358000,0x3f80,0x3f808000,0x3f808000,0x8000bf80,
0xbf80,0xbf808000,0xbf808000,0x80003f80,0x3f80,0x3f808000,0x3f808000,0x8000bf80,0xbf80,0xbf808000,0xbf808000,0x80003f80,
0xbf353f80,0x3f358000,0x3f358000,0x3f35bf80,0x3f350000,0x3f35bf80,0x3f35bf80,0xbf358000,0x3f35bf80,0xbf358000,0xbf358000,0xbf353f80,
0xbf350000,0xbf353f80,0xbf353f80,0x3f358000,0xbf803f80,0x80008000,0x80008000,0x3f80bf80,0xbf803f80,0x80008000,0x80008000,0x3f80bf80,
0xbf803f80,0x80008000,0x80008000,0x3f80bf80,0xbf803f80,0x80008000,0x80008000,0x3f80bf80,0xbf353f80,0xbf358000,0xbf358000,0x3f35bf80,
0x3f350000,0xbf353f80,0xbf353f80,0xbf358000,0x3f35bf80,0x3f358000,0x3f358000,0xbf353f80,0xbf350000,0x3f35bf80,0x3f35bf80,0x3f358000,
0x3f80,0xbf808000,0xbf808000,0x8000bf80,0xbf80,0x3f808000,0x3f808000,0x80003f80,0x3f80,0xbf808000,0xbf808000,0x8000bf80,
0xbf80,0x3f808000,0x3f808000,0x80003f80,0x3f353f80,0xbf358000,0xbf358000,0xbf35bf80,0xbf350000,0xbf35bf80,0xbf35bf80,0x3f358000,
0xbf35bf80,0x3f358000,0x3f358000,0x3f353f80,0x3f350000,0x3f353f80,0x3f353f80,0xbf358000,0x3f800000,0x0,0x3f800000,0x0,
0x3f800000,0x0,0x3f800000,0x0,0x3f800000,0x0,0x3f800000,0x0,0x3f800000,0x0,0x3f800000,0x0,
0x3f800000,0x0,0x3f7fb10f,0xbd48fb30,0x3f7ec46d,0xbdc8bd36,0x3f7d3aac,0xbe164083,0x3f7b14be,0xbe47c5c2,0x3f7853f8,0xbe78cfcc,
0x3f74fa0b,0xbe94a031,0x3f710908,0xbeac7cd4,0x3f800000,0x0,0x3f7ec46d,0xbdc8bd36,0x3f7b14be,0xbe47c5c2,0x3f74fa0b,0xbe94a031,
0x3f6c835e,0xbec3ef15,0x3f61c598,0xbef15aea,0x3f54db31,0xbf0e39da,0x3f45e403,0xbf226799,0x3f800000,0x0,0x3f7d3aac,0xbe164083,
0x3f74fa0b,0xbe94a031,0x3f676bd8,0xbedae880,0x3f54db31,0xbf0e39da,0x3f3daef9,0xbf2beb4a,0x3f226799,0xbf45e403,0x3f039c3d,0xbf5b941a,
0x3f800000,0x0,0x3f7b14be,0xbe47c5c2,0x3f6c835e,0xbec3ef15,0x3f54db31,0xbf0e39da,0x3f3504f3,0xbf3504f3,0x3f0e39da,0xbf54db31,
0x3ec3ef15,0xbf6c835e,0x3e47c5c2,0xbf7b14be,0x3f800000,0x0,0x3f7853f8,0xbe78cfcc,0x3f61c598,0xbef15aea,0x3f3daef9,0xbf2beb4a,
0x3f0e39da,0xbf54db31,0x3eac7cd4,0xbf710908,0x3dc8bd36,0xbf7ec46d,0xbe164083,0xbf7d3aac,0x3f800000,0x0,0x3f74fa0b,0xbe94a031,
0x3f54db31,0xbf0e39da,0x3f226799,0xbf45e403,0x3ec3ef15,0xbf6c835e,0x3dc8bd36,0xbf7ec46d,0xbe47c5c2,0xbf7b14be,0xbef15aea,0xbf61c598,
0x3f800000,0x0,0x3f710908,0xbeac7cd4,0x3f45e403,0xbf226799,0x3f039c3d,0xbf5b941a,0x3e47c5c2,0xbf7b14be,0xbe164083,0xbf7d3aac,
0xbef15aea,0xbf61c598,0xbf3daef9,0xbf2beb4a,0x3f800000,0x0,0x3f800000,0x0,0x3f800000,0x0,0x3f800000,0x0,
0x3f800000,0x0,0x3f800000,0x0,0x3f800000,0x0,0x3f800000,0x0,0x3f6c835e,0xbec3ef15,0x3f676bd8,0xbedae880,
0x3f61c598,0xbef15aea,0x3f5b941a,0xbf039c3d,0x3f54db31,0xbf0e39da,0x3f4d9f02,0xbf187fc0,0x3f45e403,0xbf226799,0x3f3daef9,0xbf2beb4a,
0x3f3504f3,0xbf3504f3,0x3f226799,0xbf45e403,0x3f0e39da,0xbf54db31,0x3ef15aea,0xbf61c598,0x3ec3ef15,0xbf6c835e,0x3e94a031,0xbf74fa0b,
0x3e47c5c2,0xbf7b14be,0x3dc8bd36,0xbf7ec46d,0x3ec3ef15,0xbf6c835e,0x3e78cfcc,0xbf7853f8,0x3dc8bd36,0xbf7ec46d,0xbd48fb30,0xbf7fb10f,
0xbe47c5c2,0xbf7b14be,0xbeac7cd4,0xbf710908,0xbef15aea,0xbf61c598,0xbf187fc0,0xbf4d9f02,0x0,0xbf800000,0xbe47c5c2,0xbf7b14be,
0xbec3ef15,0xbf6c835e,0xbf0e39da,0xbf54db31,0xbf3504f3,0xbf3504f3,0xbf54db31,0xbf0e39da,0xbf6c835e,0xbec3ef15,0xbf7b14be,0xbe47c5c2,
0xbec3ef15,0xbf6c835e,0xbf187fc0,0xbf4d9f02,0xbf45e403,0xbf226799,0xbf676bd8,0xbedae880,0xbf7b14be,0xbe47c5c2,0xbf7fb10f,0x3d48fb30,
0xbf74fa0b,0x3e94a031,0xbf5b941a,0x3f039c3d,0xbf3504f3,0xbf3504f3,0xbf61c598,0xbef15aea,0xbf7b14be,0xbe47c5c2,0xbf7ec46d,0x3dc8bd36,
0xbf6c835e,0x3ec3ef15,0xbf45e403,0x3f226799,0xbf0e39da,0x3f54db31,0xbe94a031,0x3f74fa0b,0xbf6c835e,0xbec3ef15,0xbf7fb10f,0xbd48fb30,
0xbf74fa0b,0x3e94a031,0xbf4d9f02,0x3f187fc0,0xbf0e39da,0x3f54db31,0xbe78cfcc,0x3f7853f8,0x3dc8bd36,0x3f7ec46d,0x3edae880,0x3f676bd8,
0x80003f80,0x3f800000,0x3f800000,0xbf80,0x3ec43f6d,0x3f6dbec4,0x3f6dbec4,0xbec4bf6d,0x3f353f35,0x3f35bf35,0x3f35bf35,0xbf35bf35,
0x3f6d3ec4,0x3ec4bf6d,0x3ec4bf6d,0xbf6dbec4,0x80003f80,0x3f800000,0xbf800000,0x3f80,0x3f6d3ec4,0x3ec4bf6d,0xbec43f6d,0x3f6d3ec4,
0x3f35bf35,0xbf35bf35,0x3f353f35,0x3f35bf35,0xbec4bf6d,0xbf6d3ec4,0x3f6dbec4,0xbec4bf6d,0x80003f80,0x3f800000,0x3f800000,0xbf80,
0x3f6dbec4,0xbec4bf6d,0xbec4bf6d,0xbf6d3ec4,0xbf35bf35,0xbf353f35,0xbf353f35,0x3f353f35,0xbec43f6d,0x3f6d3ec4,0x3f6d3ec4,0x3ec4bf6d,
0x80003f80,0x3f800000,0xbf800000,0x3f80,0x3ec4bf6d,0xbf6dbec4,0x3f6d3ec4,0x3ec4bf6d,0xbf353f35,0x3f353f35,0xbf35bf35,0xbf353f35,
0x3f6dbec4,0xbec4bf6d,0x3ec43f6d,0x3f6dbec4,0x80003f80,0x3f800000,0x3f800000,0xbf80,0xbec4bf6d,0xbf6d3ec4,0xbf6d3ec4,0x3ec43f6d,
0x3f353f35,0x3f35bf35,0x3f35bf35,0xbf35bf35,0xbf6dbec4,0xbec43f6d,0xbec43f6d,0x3f6d3ec4,0x80003f80,0x3f800000,0xbf800000,0x3f80,
0xbf6dbec4,0xbec43f6d,0x3ec4bf6d,0xbf6dbec4,0x3f35bf35,0xbf35bf35,0x3f353f35,0x3f35bf35,0x3ec43f6d,0x3f6dbec4,0xbf6d3ec4,0x3ec43f6d,
0x80003f80,0x3f800000,0x3f800000,0xbf80,0xbf6d3ec4,0x3ec43f6d,0x3ec43f6d,0x3f6dbec4,0xbf35bf35,0xbf353f35,0xbf353f35,0x3f353f35,
0x3ec4bf6d,0xbf6dbec4,0xbf6dbec4,0xbec43f6d,0x80003f80,0x3f800000,0xbf800000,0x3f80,0xbec43f6d,0x3f6d3ec4,0xbf6dbec4,0xbec43f6d,
0xbf353f35,0x3f353f35,0xbf35bf35,0xbf353f35,0xbf6d3ec4,0x3ec43f6d,0xbec4bf6d,0xbf6d3ec4,0x3f803f80,0x80008000,0x80008000,0xbf80bf80,
0x3f803f80,0x80008000,0x80008000,0xbf80bf80,0x3f803f80,0x80008000,0x80008000,0xbf80bf80,0x3f803f80,0x80008000,0x80008000,0xbf80bf80,
0x3ec43f6d,0x3f6d3ec4,0x3f6d3ec4,0xbec4bf6d,0xbf6dbec4,0x3ec43f6d,0x3ec43f6d,0x3f6d3ec4,0xbec4bf6d,0xbf6dbec4,0xbf6dbec4,0x3ec43f6d,
0x3f6d3ec4,0xbec4bf6d,0xbec4bf6d,0xbf6dbec4,0xbf353f35,0x3f353f35,0x3f353f35,0x3f35bf35,0x3f35bf35,0xbf35bf35,0xbf35bf35,0xbf353f35,
0xbf353f35,0x3f353f35,0x3f353f35,0x3f35bf35,0x3f35bf35,0xbf35bf35,0xbf35bf35,0xbf353f35,0xbf6d3ec4,0xbec43f6d,0xbec43f6d,0x3f6dbec4,
0xbec43f6d,0x3f6dbec4,0x3f6dbec4,0x3ec4bf6d,0x3f6dbec4,0x3ec4bf6d,0x3ec4bf6d,0xbf6d3ec4,0x3ec4bf6d,0xbf6d3ec4,0xbf6d3ec4,0xbec43f6d,
0x0,0xbf803f80,0xbf803f80,0x80008000,0x0,0xbf803f80,0xbf803f80,0x80008000,0x0,0xbf803f80,0xbf803f80,0x80008000,
0x0,0xbf803f80,0xbf803f80,0x80008000,0x3f6dbec4,0xbec43f6d,0xbec43f6d,0xbf6d3ec4,0x3ec4bf6d,0x3f6dbec4,0x3f6dbec4,0xbec43f6d,
0xbf6d3ec4,0x3ec4bf6d,0x3ec4bf6d,0x3f6dbec4,0xbec43f6d,0xbf6d3ec4,0xbf6d3ec4,0x3ec4bf6d,0x3f35bf35,0x3f353f35,0x3f353f35,0xbf353f35,
0xbf353f35,0xbf35bf35,0xbf35bf35,0x3f35bf35,0x3f35bf35,0x3f353f35,0x3f353f35,0xbf353f35,0xbf353f35,0xbf35bf35,0xbf35bf35,0x3f35bf35,
0xbec4bf6d,0x3f6d3ec4,0x3f6d3ec4,0x3ec43f6d,0x3f6d3ec4,0x3ec43f6d,0x3ec43f6d,0xbf6dbec4,0x3ec43f6d,0xbf6dbec4,0xbf6dbec4,0xbec4bf6d,
0xbf6dbec4,0xbec4bf6d,0xbec4bf6d,0x3f6d3ec4,0x3f800000,0x0,0x3f7fec43,0xbcc90ab0,0x3f7fb10f,0xbd48fb30,0x3f7f4e6d,0xbd96a905,
0x3f7ec46d,0xbdc8bd36,0x3f7e1324,0xbdfab273,0x3f7d3aac,0xbe164083,0x3f7c3b28,0xbe2f10a2,0x3f800000,0x0,0x3f7f4e6d,0xbd96a905,
0x3f7d3aac,0xbe164083,0x3f79c79d,0xbe605c13,0x3f74fa0b,0xbe94a031,0x3f6ed89e,0xbeb8442a,0x3f676bd8,0xbedae880,0x3f5ebe05,0xbefc5d27,
0x3f800000,0x0,0x3f7e1324,0xbdfab273,0x3f7853f8,0xbe78cfcc,0x3f6ed89e,0xbeb8442a,0x3f61c598,0xbef15aea,0x3f514d3d,0xbf13682a,
0x3f3daef9,0xbf2beb4a,0x3f273656,0xbf41d870,0x3f800000,0x0,0x3f7c3b28,0xbe2f10a2,0x3f710908,0xbeac7cd4,0x3f5ebe05,0xbefc5d27,
0x3f45e403,0xbf226799,0x3f273656,0xbf41d870,0x3f039c3d,0xbf5b941a,0x3eb8442a,0xbf6ed89e,0x3f800000,0x0,0x3f79c79d,0xbe605c13,
0x3f676bd8,0xbedae880,0x3f49d112,0xbf1d7fd1,0x3f226799,0xbf45e403,0x3ee63375,0xbf64aa59,0x3e78cfcc,0xbf7853f8,0x3cc90ab0,0xbf7fec43,
0x3f800000,0x0,0x3f76ba07,0xbe888e93,0x3f5b941a,0xbf039c3d,0x3f3085bb,0xbf396842,0x3ef15aea,0xbf61c598,0x3e605c13,0xbf79c79d,
0xbd48fb30,0xbf7fb10f,0xbea09ae5,0xbf731447,0x3f800000,0x0,0x3f731447,0xbea09ae5,0x3f4d9f02,0xbf187fc0,0x3f13682a,0xbf514d3d,
0x3e94a031,0xbf74fa0b,0xbcc90ab0,0xbf7fec43,0xbeac7cd4,0xbf710908,0xbf1d7fd1,0xbf49d112,0x3f800000,0x0,0x3f6ed89e,0xbeb8442a,
0x3f3daef9,0xbf2beb4a,0x3ee63375,0xbf64aa59,0x3dc8bd36,0xbf7ec46d,0xbe888e93,0xbf76ba07,0xbf187fc0,0xbf4d9f02,0xbf584853,0xbf08f59b,
0x3f7b14be,0xbe47c5c2,0x3f79c79d,0xbe605c13,0x3f7853f8,0xbe78cfcc,0x3f76ba07,0xbe888e93,0x3f74fa0b,0xbe94a031,0x3f731447,0xbea09ae5,
0x3f710908,0xbeac7cd4,0x3f6ed89e,0xbeb8442a,0x3f54db31,0xbf0e39da,0x3f49d112,0xbf1d7fd1,0x3f3daef9,0xbf2beb4a,0x3f3085bb,0xbf396842,
0x3f226799,0xbf45e403,0x3f13682a,0xbf514d3d,0x3f039c3d,0xbf5b941a,0x3ee63375,0xbf64aa59,0x3f0e39da,0xbf54db31,0x3ee63375,0xbf64aa59,
0x3eac7cd4,0xbf710908,0x3e605c13,0xbf79c79d,0x3dc8bd36,0xbf7ec46d,0xbcc90ab0,0xbf7fec43,0xbe164083,0xbf7d3aac,0xbe888e93,0xbf76ba07,
0x3e47c5c2,0xbf7b14be,0x3cc90ab0,0xbf7fec43,0xbe164083,0xbf7d3aac,0xbea09ae5,0xbf731447,0xbef15aea,0xbf61c598,0xbf1d7fd1,0xbf49d112,
0xbf3daef9,0xbf2beb4a,0xbf584853,0xbf08f59b,0xbe47c5c2,0xbf7b14be,0xbecf7bca,0xbf6a09a7,0xbf187fc0,0xbf4d9f02,0xbf41d870,0xbf273656,
0xbf61c598,0xbef15aea,0xbf76ba07,0xbe888e93,0xbf7fb10f,0xbd48fb30,0xbf7c3b28,0x3e2f10a2,0xbf0e39da,0xbf54db31,0xbf41d870,0xbf273656,
0xbf676bd8,0xbedae880,0xbf7c3b28,0xbe2f10a2,0xbf7ec46d,0x3dc8bd36,0xbf6ed89e,0x3eb8442a,0xbf4d9f02,0x3f187fc0,0xbf1d7fd1,0x3f49d112,
0xbf54db31,0xbf0e39da,0xbf76ba07,0xbe888e93,0xbf7fb10f,0x3d48fb30,0xbf6ed89e,0x3eb8442a,0xbf45e403,0x3f226799,0xbf08f59b,0x3f584853,
0xbe78cfcc,0x3f7853f8,0x3d96a905,0x3f7f4e6d,0xbf7b14be,0xbe47c5c2,0xbf7c3b28,0x3e2f10a2,0xbf5b941a,0x3f039c3d,0xbf1d7fd1,0x3f49d112,
0xbe94a031,0x3f74fa0b,0x3d96a905,0x3f7f4e6d,0x3edae880,0x3f676bd8,0x3f396842,0x3f3085bb,0x80003f80,0x80003f80,0x80003f80,0x80003f80,
0x80003f80,0x80003f80,0x80003f80,0x80003f80,0x80003f80,0x80003f80,0x80003f80,0x80003f80,0x80003f80,0x80003f80,0x80003f80,0x80003f80,
0x3f800000,0x3f800000,0x3f800000,0x3f800000,0x3f800000,0x3f800000,0x3f800000,0x3f800000,0x3f800000,0x3f800000,0x3f800000,0x3f800000,
0x3f800000,0x3f800000,0x3f800000,0x3f800000,0x80003f80,0x3f353f35,0x80003f80,0x3f353f35,0x3f800000,0x3f35bf35,0x3f800000,0x3f35bf35,
0x8000bf80,0xbf35bf35,0x8000bf80,0xbf35bf35,0xbf800000,0xbf353f35,0xbf800000,0xbf353f35,0x3f800000,0x3f35bf35,0x3f800000,0x3f35bf35,
0xbf80,0xbf35bf35,0xbf80,0xbf35bf35,0xbf800000,0xbf353f35,0xbf800000,0xbf353f35,0x3f80,0x3f353f35,0x3f80,0x3f353f35,
0x80003f80,0x3f800000,0x80003f80,0x3f800000,0x8000bf80,0xbf800000,0x8000bf80,0xbf800000,0x80003f80,0x3f800000,0x80003f80,0x3f800000,
0x8000bf80,0xbf800000,0x8000bf80,0xbf800000,0x3f800000,0xbf80,0x3f800000,0xbf80,0xbf800000,0x3f80,0xbf800000,0x3f80,
0x3f800000,0xbf80,0x3f800000,0xbf80,0xbf800000,0x3f80,0xbf800000,0x3f80,0x80003f80,0x3f35bf35,0x80003f80,0x3f35bf35,
0xbf800000,0x3f353f35,0xbf800000,0x3f353f35,0x8000bf80,0xbf353f35,0x8000bf80,0xbf353f35,0x3f800000,0xbf35bf35,0x3f800000,0xbf35bf35,
0x3f800000,0xbf35bf35,0x3f800000,0xbf35bf35,0x3f80,0x3f35bf35,0x3f80,0x3f35bf35,0xbf800000,0x3f353f35,0xbf800000,0x3f353f35,
0xbf80,0xbf353f35,0xbf80,0xbf353f35,0x80003f80,0x3ec43f6d,0x8000bf80,0xbec4bf6d,0x3f353f35,0x3f6d3ec4,0xbf35bf35,0xbf6dbec4,
0x3f800000,0x3f6dbec4,0xbf800000,0xbf6d3ec4,0x3f35bf35,0x3ec4bf6d,0xbf353f35,0xbec43f6d,0x3f800000,0x3f6dbec4,0xbf800000,0xbf6d3ec4,
0x3f35bf35,0x3ec4bf6d,0xbf353f35,0xbec43f6d,0xbf80,0xbec4bf6d,0x3f80,0x3ec43f6d,0xbf35bf35,0xbf6dbec4,0x3f353f35,0x3f6d3ec4,
0x80003f80,0x3f6d3ec4,0x8000bf80,0xbf6dbec4,0x3f35bf35,0xbec4bf6d,0xbf353f35,0x3ec43f6d,0xbf800000,0xbec43f6d,0x3f800000,0x3ec4bf6d,
0x3f353f35,0x3f6dbec4,0xbf35bf35,0xbf6d3ec4,0x3f800000,0x3ec4bf6d,0xbf800000,0xbec43f6d,0xbf35bf35,0xbf6d3ec4,0x3f353f35,0x3f6dbec4,
0x3f80,0x3f6d3ec4,0xbf80,0xbf6dbec4,0x3f35bf35,0xbec4bf6d,0xbf353f35,0x3ec43f6d,0x80003f80,0x3f6dbec4,0x8000bf80,0xbf6d3ec4,
0xbf35bf35,0xbec43f6d,0x3f353f35,0x3ec4bf6d,0x3f800000,0xbec4bf6d,0xbf800000,0x3ec43f6d,0xbf353f35,0x3f6d3ec4,0x3f35bf35,0xbf6dbec4,
0x3f800000,0xbec4bf6d,0xbf800000,0x3ec43f6d,0xbf353f35,0x3f6d3ec4,0x3f35bf35,0xbf6dbec4,0xbf80,0xbf6d3ec4,0x3f80,0x3f6dbec4,
0x3f353f35,0x3ec4bf6d,0xbf35bf35,0xbec43f6d,0x80003f80,0x3ec4bf6d,0x8000bf80,0xbec43f6d,0xbf353f35,0x3f6dbec4,0x3f35bf35,0xbf6d3ec4,
0xbf800000,0x3f6d3ec4,0x3f800000,0xbf6dbec4,0xbf35bf35,0x3ec43f6d,0x3f353f35,0xbec4bf6d,0x3f800000,0xbf6dbec4,0xbf800000,0x3f6d3ec4,
0x3f353f35,0xbec4bf6d,0xbf35bf35,0x3ec43f6d,0x3f80,0x3ec4bf6d,0xbf80,0xbec43f6d,0xbf353f35,0x3f6dbec4,0x3f35bf35,0xbf6d3ec4,
0x80003f80,0x8000bf80,0x80003f80,0x8000bf80,0x80003f80,0x8000bf80,0x80003f80,0x8000bf80,0x80003f80,0x8000bf80,0x80003f80,0x8000bf80,
0x80003f80,0x8000bf80,0x80003f80,0x8000bf80,0x3f800000,0xbf800000,0x3f800000,0xbf800000,0x3f800000,0xbf800000,0x3f800000,0xbf800000,
0x3f800000,0xbf800000,0x3f800000,0xbf800000,0x3f800000,0xbf800000,0x3f800000,0xbf800000,0x80003f80,0xbf35bf35,0x80003f80,0xbf35bf35,
0x3f800000,0xbf353f35,0x3f800000,0xbf353f35,0x8000bf80,0x3f353f35,0x8000bf80,0x3f353f35,0xbf800000,0x3f35bf35,0xbf800000,0x3f35bf35,
0x3f800000,0xbf353f35,0x3f800000,0xbf353f35,0xbf80,0x3f353f35,0xbf80,0x3f353f35,0xbf800000,0x3f35bf35,0xbf800000,0x3f35bf35,
0x3f80,0xbf35bf35,0x3f80,0xbf35bf35,0x80003f80,0xbf800000,0x80003f80,0xbf800000,0x8000bf80,0x3f800000,0x8000bf80,0x3f800000,
0x80003f80,0xbf800000,0x80003f80,0xbf800000,0x8000bf80,0x3f800000,0x8000bf80,0x3f800000,0x3f800000,0x3f80,0x3f800000,0x3f80,
0xbf800000,0xbf80,0xbf800000,0xbf80,0x3f800000,0x3f80,0x3f800000,0x3f80,0xbf800000,0xbf80,0xbf800000,0xbf80,
0x80003f80,0xbf353f35,0x80003f80,0xbf353f35,0xbf800000,0xbf35bf35,0xbf800000,0xbf35bf35,0x8000bf80,0x3f35bf35,0x8000bf80,0x3f35bf35,
0x3f800000,0x3f353f35,0x3f800000,0x3f353f35,0x3f800000,0x3f353f35,0x3f800000,0x3f353f35,0x3f80,0xbf353f35,0x3f80,0xbf353f35,
0xbf800000,0xbf35bf35,0xbf800000,0xbf35bf35,0xbf80,0x3f35bf35,0xbf80,0x3f35bf35,0x80003f80,0xbec4bf6d,0x8000bf80,0x3ec43f6d,
0x3f353f35,0xbf6dbec4,0xbf35bf35,0x3f6d3ec4,0x3f800000,0xbf6d3ec4,0xbf800000,0x3f6dbec4,0x3f35bf35,0xbec43f6d,0xbf353f35,0x3ec4bf6d,
0x3f800000,0xbf6d3ec4,0xbf800000,0x3f6dbec4,0x3f35bf35,0xbec43f6d,0xbf353f35,0x3ec4bf6d,0xbf80,0x3ec43f6d,0x3f80,0xbec4bf6d,
0xbf35bf35,0x3f6d3ec4,0x3f353f35,0xbf6dbec4,0x80003f80,0xbf6dbec4,0x8000bf80,0x3f6d3ec4,0x3f35bf35,0x3ec43f6d,0xbf353f35,0xbec4bf6d,
0xbf800000,0x3ec4bf6d,0x3f800000,0xbec43f6d,0x3f353f35,0xbf6d3ec4,0xbf35bf35,0x3f6dbec4,0x3f800000,0xbec43f6d,0xbf800000,0x3ec4bf6d,
0xbf35bf35,0x3f6dbec4,0x3f353f35,0xbf6d3ec4,0x3f80,0xbf6dbec4,0xbf80,0x3f6d3ec4,0x3f35bf35,0x3ec43f6d,0xbf353f35,0xbec4bf6d,
0x80003f80,0xbf6d3ec4,0x8000bf80,0x3f6dbec4,0xbf35bf35,0x3ec4bf6d,0x3f353f35,0xbec43f6d,0x3f800000,0x3ec43f6d,0xbf800000,0xbec4bf6d,
0xbf353f35,0xbf6dbec4,0x3f35bf35,0x3f6d3ec4,0x3f800000,0x3ec43f6d,0xbf800000,0xbec4bf6d,0xbf353f35,0xbf6dbec4,0x3f35bf35,0x3f6d3ec4,
0xbf80,0x3f6dbec4,0x3f80,0xbf6d3ec4,0x3f353f35,0xbec43f6d,0xbf35bf35,0x3ec4bf6d,0x80003f80,0xbec43f6d,0x8000bf80,0x3ec4bf6d,
0xbf353f35,0xbf6d3ec4,0x3f35bf35,0x3f6dbec4,0xbf800000,0xbf6dbec4,0x3f800000,0x3f6d3ec4,0xbf35bf35,0xbec4bf6d,0x3f353f35,0x3ec43f6d,
0x3f800000,0x3f6d3ec4,0xbf800000,0xbf6dbec4,0x3f353f35,0x3ec43f6d,0xbf35bf35,0xbec4bf6d,0x3f80,0xbec43f6d,0xbf80,0x3ec4bf6d,
0xbf353f35,0xbf6d3ec4,0x3f35bf35,0x3f6dbec4,
};
constexpr int TB_F = 0, TB_E = 512, TB_P2 = 1024;

enum { C_EP = 0, C_Z1 = 32, C_Z2 = 96, C_H3 = 128, C_U = 160, C_TOTAL = 256 };
struct Scratch {
  unsigned cnt[C_TOTAL];
  uint32_t moda[8 * 2 * D_];
  uint32_t mod[4 * D_ + 256];
  uint32_t z1[120 * 5120];
  uint32_t z2[128 * 4800];
  uint32_t x1[S_ * D_ / 2];
  uint8_t h3[32 * 18 * 4096];
  uint8_t u[72 * D_ * 128];
  uint4 part[128 * 1152];
};
__device__ __align__(1024) Scratch g_s;

#define PF2 8
#define PF2K 16
#define HOLDA 3
#define GOAT 1
#define HOLD1 0
#define XPOS 0
#define HW bulk_commit_wait
#define H3W 0
#define X1K 10
#define PEEK 1
#define H3G 2
#define PFF 2
#define NG1 2

#define FAILCNT(k) do {} while (0)
#define CK(k) do {} while (0)
#define CKX(k) do {} while (0)
#define TS(k) do {} while (0)
#define TSC(k) do {} while (0)
struct Maps { CUtensorMap z1, z2[2], w1a, w1b, h3[2], w2, x1, out, wf[4], wm; };
struct Params {
  const __nv_bfloat16 *x, *c, *wmod;
  Scratch* s;
  const uint4* tab;
  const __nv_bfloat16 *wr, *wi, *w1, *w2, *b1, *b2;
};

__device__ __forceinline__ uint32_t smem_u32(const void* p) { return (uint32_t)__cvta_generic_to_shared(p); }
__device__ __forceinline__ void mbar_init(uint32_t b, int c) { asm volatile("mbarrier.init.shared::cta.b64 [%0], %1;" ::"r"(b), "r"(c)); }
__device__ __forceinline__ void mbar_expect(uint32_t b, int bytes) { asm volatile("mbarrier.arrive.expect_tx.shared::cta.b64 _, [%0], %1;" ::"r"(b), "r"(bytes) : "memory"); }
__device__ __forceinline__ void mbar_arrive(uint32_t b) { asm volatile("mbarrier.arrive.shared::cta.b64 _, [%0];" ::"r"(b) : "memory"); }
#define MBAR_WAIT(SEM)                                                                                                         \
  asm volatile("{\n.reg .pred p;\n.reg .u32 it;\nmov.u32 it, 0;\nW:\nmbarrier.try_wait.parity" SEM ".shared::cta.b64 p, [%0], %1;\n" \
               "@p bra.uni D;\nadd.u32 it, it, 1;\nsetp.lt.u32 p, it, 0x400000;\n@p bra.uni W;\ntrap;\nD:\n}" ::"r"(b), "r"(ph) : "memory")
__device__ __forceinline__ void mbar_wait(uint32_t b, int ph) { MBAR_WAIT(""); }
__device__ __forceinline__ uint32_t mbar_test(uint32_t b, int ph) {
  uint32_t ok;
  asm volatile("{\n.reg .pred p;\nmbarrier.test_wait.parity.shared::cta.b64 p, [%1], %2;\nselp.u32 %0, 1, 0, p;\n}\n" : "=r"(ok) : "r"(b), "r"(ph) : "memory");
  return ok;
}
__device__ __forceinline__ void tma2d(uint32_t dst, const CUtensorMap* m, int c0, int c1, uint32_t bar) {
  asm volatile("cp.async.bulk.tensor.2d.shared::cluster.global.mbarrier::complete_tx::bytes [%0], [%1, {%3, %4}], [%2];" ::"r"(dst), "l"(m), "r"(bar), "r"(c0), "r"(c1) : "memory");
}
__device__ __forceinline__ uint64_t pol_ef() { uint64_t p; asm("createpolicy.fractional.L2::evict_first.b64 %0, 1.0;" : "=l"(p)); return p; }
__device__ __forceinline__ void tma3d_ef(uint32_t dst, const CUtensorMap* m, int c1, int c2, uint32_t bar) {
  asm volatile("cp.async.bulk.tensor.3d.shared::cluster.global.mbarrier::complete_tx::bytes.L2::cache_hint [%0], [%1, {%3, %4, %5}], [%2], %6;" ::"r"(dst), "l"(m), "r"(bar), "r"(0), "r"(c1), "r"(c2), "l"(pol_ef()) : "memory");
}
__device__ __forceinline__ void tma4d_ef(uint32_t dst, const CUtensorMap* m, int c1, int c2, int c3, uint32_t bar) {
  asm volatile("cp.async.bulk.tensor.4d.shared::cluster.global.mbarrier::complete_tx::bytes.L2::cache_hint [%0], [%1, {%3, %7, %4, %5}], [%2], %6;" ::"r"(dst), "l"(m), "r"(bar), "r"(0), "r"(c2), "r"(c3), "l"(pol_ef()), "r"(c1) : "memory");
}
__device__ __forceinline__ void bulk_ld(uint32_t dst, const void* src, int bytes, uint32_t bar) {
  asm volatile("cp.async.bulk.shared::cluster.global.mbarrier::complete_tx::bytes [%0], [%1], %2, [%3];" ::"r"(dst), "l"(src), "r"(bytes), "r"(bar) : "memory");
}
__device__ __forceinline__ void bulk_st(void* dst, uint32_t src, int bytes) {
  asm volatile("cp.async.bulk.global.shared::cta.bulk_group [%0], [%1], %2;" ::"l"(dst), "r"(src), "r"(bytes) : "memory");
}
__device__ __forceinline__ void tma_st2d(const CUtensorMap* m, uint32_t src, int c0, int c1) {
  asm volatile("cp.async.bulk.tensor.2d.global.shared::cta.bulk_group [%0, {%2, %3}], [%1];" ::"l"(m), "r"(src), "r"(c0), "r"(c1) : "memory");
}
__device__ __forceinline__ void tma_st3d(const CUtensorMap* m, uint32_t src, int c0, int c1, int c2) {
  asm volatile("cp.async.bulk.tensor.3d.global.shared::cta.bulk_group [%0, {%2, %3, %4}], [%1];" ::"l"(m), "r"(src), "r"(c0), "r"(c1), "r"(c2) : "memory");
}
__device__ __forceinline__ void bulk_commit_wait_read() {
  asm volatile("cp.async.bulk.commit_group;" ::: "memory");
  asm volatile("cp.async.bulk.wait_group.read 0;" ::: "memory");
}
__device__ __forceinline__ void bulk_commit_wait() {
  asm volatile("cp.async.bulk.commit_group;" ::: "memory");
  asm volatile("cp.async.bulk.wait_group 0;" ::: "memory");
}
__device__ __forceinline__ void prefetch_l2(const void* p, int bytes) {
  asm volatile("cp.async.bulk.prefetch.L2.global [%0], %1;" ::"l"(p), "r"(bytes) : "memory");
}
__device__ __forceinline__ void wg_fence() { asm volatile("wgmma.fence.sync.aligned;" ::: "memory"); }
__device__ __forceinline__ void wg_commit() { asm volatile("wgmma.commit_group.sync.aligned;" ::: "memory"); }
template <int N> __device__ __forceinline__ void wg_wait() { asm volatile("wgmma.wait_group.sync.aligned %0;" ::"n"(N) : "memory"); }
template <int N> __device__ __forceinline__ void reg_fence(float (&d)[N]) {
#pragma unroll
  for (int i = 0; i < N; i++) asm volatile("" : "+f"(d[i])::"memory");
}
__device__ __forceinline__ void fence_async_smem() { asm volatile("fence.proxy.async.shared::cta;" ::: "memory"); }
__device__ __forceinline__ void fence_async_glb() { asm volatile("fence.proxy.async.global;" ::: "memory"); }
__device__ __forceinline__ uint32_t ld_rlx(const void* p) { uint32_t v; asm volatile("ld.relaxed.gpu.global.b32 %0, [%1];" : "=r"(v) : "l"(p) : "memory"); return v; }
__device__ __forceinline__ uint2 ld_rlx2(const void* p) { uint2 v; asm volatile("ld.relaxed.gpu.global.v2.b32 {%0,%1}, [%2];" : "=r"(v.x), "=r"(v.y) : "l"(p) : "memory"); return v; }
__device__ __forceinline__ uint4 ld_rlx4(const void* p) { uint4 v; asm volatile("ld.relaxed.gpu.global.v4.b32 {%0,%1,%2,%3}, [%4];" : "=r"(v.x), "=r"(v.y), "=r"(v.z), "=r"(v.w) : "l"(p) : "memory"); return v; }
__device__ __forceinline__ uint32_t ld_nc(const void* p) { uint32_t v; asm volatile("ld.global.nc.L1::no_allocate.b32 %0, [%1];" : "=r"(v) : "l"(p) : "memory"); return v; }
__device__ __forceinline__ uint4 ld_nc4(const void* p) { uint4 v; asm volatile("ld.global.nc.v4.b32 {%0,%1,%2,%3}, [%4];" : "=r"(v.x), "=r"(v.y), "=r"(v.z), "=r"(v.w) : "l"(p) : "memory"); return v; }
__device__ __forceinline__ uint32_t lds(uint32_t a) { uint32_t v; asm volatile("ld.shared.b32 %0, [%1];" : "=r"(v) : "r"(a) : "memory"); return v; }
__device__ __forceinline__ uint2 lds2(uint32_t a) { uint2 v; asm volatile("ld.shared.v2.b32 {%0,%1}, [%2];" : "=r"(v.x), "=r"(v.y) : "r"(a) : "memory"); return v; }
__device__ __forceinline__ uint4 lds4(uint32_t a) { uint4 v; asm volatile("ld.shared.v4.b32 {%0,%1,%2,%3}, [%4];" : "=r"(v.x), "=r"(v.y), "=r"(v.z), "=r"(v.w) : "r"(a) : "memory"); return v; }
__device__ __forceinline__ float lds_bf(uint32_t a) { uint32_t v; asm volatile("ld.shared.u16 %0, [%1];" : "=r"(v) : "r"(a) : "memory"); return __uint_as_float(v << 16); }
__device__ __forceinline__ void sts(uint32_t a, uint32_t v) { asm volatile("st.shared.b32 [%0], %1;" ::"r"(a), "r"(v) : "memory"); }
__device__ __forceinline__ void sts2(uint32_t a, uint32_t v0, uint32_t v1) { asm volatile("st.shared.v2.b32 [%0], {%1,%2};" ::"r"(a), "r"(v0), "r"(v1) : "memory"); }
__device__ __forceinline__ void sts4(uint32_t a, uint32_t v0, uint32_t v1, uint32_t v2, uint32_t v3) { asm volatile("st.shared.v4.b32 [%0], {%1,%2,%3,%4};" ::"r"(a), "r"(v0), "r"(v1), "r"(v2), "r"(v3) : "memory"); }
__device__ __forceinline__ void bar_sync(int id, int n) { asm volatile("bar.sync %0, %1;" ::"r"(id), "r"(n) : "memory"); }
__device__ __forceinline__ void bar_arrive(int id, int n) { asm volatile("bar.arrive %0, %1;" ::"r"(id), "r"(n) : "memory"); }
__device__ __forceinline__ void red_add(unsigned* p, unsigned v) { asm volatile("red.relaxed.gpu.global.add.u32 [%0], %1;" ::"l"(p), "r"(v) : "memory"); }
__device__ __forceinline__ bool any(bool p) { return __any_sync(0xffffffffu, p); }
constexpr int SPIN_MAX = 1 << 20;
__device__ __forceinline__ void wait_cnt(const unsigned* p, unsigned target) {
  int it = 0;
  while (any((int)(ld_rlx(p) - target) < 0) && ++it < SPIN_MAX) {}
}
__device__ __forceinline__ uint32_t pack_bf16(float lo, float hi) { uint32_t r; asm("cvt.rn.bf16x2.f32 %0, %1, %2;" : "=r"(r) : "f"(hi), "f"(lo)); return r; }
__device__ __forceinline__ float bf_lo(uint32_t v) { return __uint_as_float(v << 16); }
__device__ __forceinline__ float bf_hi(uint32_t v) { return __uint_as_float(v & 0xffff0000u); }
__device__ __forceinline__ uint32_t hadd2(uint32_t a, uint32_t b) { uint32_t r; asm("add.rn.bf16x2 %0, %1, %2;" : "=r"(r) : "r"(a), "r"(b)); return r; }
__device__ __forceinline__ uint32_t hmul2(uint32_t a, uint32_t b) { uint32_t r; asm("mul.rn.bf16x2 %0, %1, %2;" : "=r"(r) : "r"(a), "r"(b)); return r; }
__device__ __forceinline__ uint32_t hfma2(uint32_t a, uint32_t b, uint32_t c) { uint32_t r; asm("fma.rn.bf16x2 %0, %1, %2, %3;" : "=r"(r) : "r"(a), "r"(b), "r"(c)); return r; }
__device__ __forceinline__ float rbf(float x) { uint32_t r; asm("cvt.rn.bf16x2.f32 %0, %1, %2;" : "=r"(r) : "f"(x), "f"(0.0f)); return __uint_as_float(r); }
__device__ __forceinline__ void stmatrix4(uint32_t a, uint32_t r0, uint32_t r1, uint32_t r2, uint32_t r3) {
  asm volatile("stmatrix.sync.aligned.m8n8.x4.shared.b16 [%0], {%1,%2,%3,%4};" ::"r"(a), "r"(r0), "r"(r1), "r"(r2), "r"(r3) : "memory");
}
__device__ __forceinline__ void stmatrix2(uint32_t a, uint32_t r0, uint32_t r1) {
  asm volatile("stmatrix.sync.aligned.m8n8.x2.shared.b16 [%0], {%1,%2};" ::"r"(a), "r"(r0), "r"(r1) : "memory");
}
__device__ __forceinline__ void stmatrix4t(uint32_t a, uint32_t r0, uint32_t r1, uint32_t r2, uint32_t r3) {
  asm volatile("stmatrix.sync.aligned.m8n8.x4.trans.shared.b16 [%0], {%1,%2,%3,%4};" ::"r"(a), "r"(r0), "r"(r1), "r"(r2), "r"(r3) : "memory");
}
__device__ __forceinline__ uint32_t movm(uint32_t a) { uint32_t r; asm("movmatrix.sync.aligned.m8n8.trans.b16 %0, %1;" : "=r"(r) : "r"(a)); return r; }
template <bool ACC> __device__ __forceinline__ void mma16(float* d, uint32_t a0, uint32_t a1, uint32_t a2, uint32_t a3, uint32_t b0, uint32_t b1) {
  if (ACC) asm("mma.sync.aligned.m16n8k16.row.col.f32.bf16.bf16.f32 {%0,%1,%2,%3}, {%4,%5,%6,%7}, {%8,%9}, {%0,%1,%2,%3};"
               : "+f"(d[0]), "+f"(d[1]), "+f"(d[2]), "+f"(d[3]) : "r"(a0), "r"(a1), "r"(a2), "r"(a3), "r"(b0), "r"(b1));
  else asm("mma.sync.aligned.m16n8k16.row.col.f32.bf16.bf16.f32 {%0,%1,%2,%3}, {%4,%5,%6,%7}, {%8,%9}, {%10,%10,%10,%10};"
           : "=f"(d[0]), "=f"(d[1]), "=f"(d[2]), "=f"(d[3]) : "r"(a0), "r"(a1), "r"(a2), "r"(a3), "r"(b0), "r"(b1), "f"(0.f));
}
__device__ __forceinline__ uint32_t pin(uint32_t v) { uint32_t r; asm volatile("shfl.sync.bfly.b32 %0, %1, 0, 31, 0xffffffff;" : "=r"(r) : "r"(v)); return r; }
template <class T> __device__ __forceinline__ T* pin(T* p) {
  const uint64_t a = reinterpret_cast<uint64_t>(p);
  return reinterpret_cast<T*>((uint64_t)pin((uint32_t)a) | ((uint64_t)pin((uint32_t)(a >> 32)) << 32));
}
__device__ __forceinline__ uint32_t upin(uint32_t v) { return __shfl_sync(0xffffffffu, v, 0); }
template <class T> __device__ __forceinline__ T* upin(T* p) {
  const uint64_t a = reinterpret_cast<uint64_t>(p);
  return reinterpret_cast<T*>((uint64_t)upin((uint32_t)a) | ((uint64_t)upin((uint32_t)(a >> 32)) << 32));
}
__device__ __forceinline__ bool elect() {
  uint32_t p;
  asm volatile("{\n.reg .pred P;\nelect.sync _|P, 0xffffffff;\nselp.u32 %0, 1, 0, P;\n}" : "=r"(p));
  return p;
}
__device__ __forceinline__ uint32_t set_tag(uint32_t w, uint32_t tag) { uint32_t r; asm("lop3.b32 %0, %1, 0xfffffffe, %2, 0xea;" : "=r"(r) : "r"(w), "r"(tag)); return r; }
__device__ __forceinline__ uint32_t diff2(uint32_t a, uint32_t b, uint32_t tag) { uint32_t r; asm("lop3.b32 %0, %1, %2, %3, 0x7e;" : "=r"(r) : "r"(a), "r"(b), "r"(tag)); return r; }
__device__ __forceinline__ float2 cmul(float2 a, float2 b) { return make_float2(a.x * b.x - a.y * b.y, a.x * b.y + a.y * b.x); }

template<int TB> __device__ __forceinline__ void wgmma_ss_160_0(float (&d)[80], uint32_t al, uint32_t ah, uint32_t bl, uint32_t bh) {
  asm volatile("{\n.reg .b64 da, db;\nmov.b64 da, {%80, %81};\nmov.b64 db, {%82, %83};\n"
    "wgmma.mma_async.sync.aligned.m64n160k16.f32.bf16.bf16 {%0,%1,%2,%3,%4,%5,%6,%7,%8,%9,%10,%11,%12,%13,%14,%15,%16,%17,%18,%19,%20,%21,%22,%23,%24,%25,%26,%27,%28,%29,%30,%31,%32,%33,%34,%35,%36,%37,%38,%39,%40,%41,%42,%43,%44,%45,%46,%47,%48,%49,%50,%51,%52,%53,%54,%55,%56,%57,%58,%59,%60,%61,%62,%63,%64,%65,%66,%67,%68,%69,%70,%71,%72,%73,%74,%75,%76,%77,%78,%79}, da, db, 1, 1, 1, 1, %84;\n}\n"
    : "+f"(d[0]),"+f"(d[1]),"+f"(d[2]),"+f"(d[3]),"+f"(d[4]),"+f"(d[5]),"+f"(d[6]),"+f"(d[7]),"+f"(d[8]),"+f"(d[9]),"+f"(d[10]),"+f"(d[11]),"+f"(d[12]),"+f"(d[13]),"+f"(d[14]),"+f"(d[15]),"+f"(d[16]),"+f"(d[17]),"+f"(d[18]),"+f"(d[19]),"+f"(d[20]),"+f"(d[21]),"+f"(d[22]),"+f"(d[23]),"+f"(d[24]),"+f"(d[25]),"+f"(d[26]),"+f"(d[27]),"+f"(d[28]),"+f"(d[29]),"+f"(d[30]),"+f"(d[31]),"+f"(d[32]),"+f"(d[33]),"+f"(d[34]),"+f"(d[35]),"+f"(d[36]),"+f"(d[37]),"+f"(d[38]),"+f"(d[39]),"+f"(d[40]),"+f"(d[41]),"+f"(d[42]),"+f"(d[43]),"+f"(d[44]),"+f"(d[45]),"+f"(d[46]),"+f"(d[47]),"+f"(d[48]),"+f"(d[49]),"+f"(d[50]),"+f"(d[51]),"+f"(d[52]),"+f"(d[53]),"+f"(d[54]),"+f"(d[55]),"+f"(d[56]),"+f"(d[57]),"+f"(d[58]),"+f"(d[59]),"+f"(d[60]),"+f"(d[61]),"+f"(d[62]),"+f"(d[63]),"+f"(d[64]),"+f"(d[65]),"+f"(d[66]),"+f"(d[67]),"+f"(d[68]),"+f"(d[69]),"+f"(d[70]),"+f"(d[71]),"+f"(d[72]),"+f"(d[73]),"+f"(d[74]),"+f"(d[75]),"+f"(d[76]),"+f"(d[77]),"+f"(d[78]),"+f"(d[79])
    : "r"(al), "r"(ah), "r"(bl), "r"(bh), "n"(TB));
}
template<int TB> __device__ __forceinline__ void wgmma_ss_144_0(float (&d)[80], uint32_t al, uint32_t ah, uint32_t bl, uint32_t bh) {
  asm volatile("{\n.reg .b64 da, db;\nmov.b64 da, {%72, %73};\nmov.b64 db, {%74, %75};\n"
    "wgmma.mma_async.sync.aligned.m64n144k16.f32.bf16.bf16 {%0,%1,%2,%3,%4,%5,%6,%7,%8,%9,%10,%11,%12,%13,%14,%15,%16,%17,%18,%19,%20,%21,%22,%23,%24,%25,%26,%27,%28,%29,%30,%31,%32,%33,%34,%35,%36,%37,%38,%39,%40,%41,%42,%43,%44,%45,%46,%47,%48,%49,%50,%51,%52,%53,%54,%55,%56,%57,%58,%59,%60,%61,%62,%63,%64,%65,%66,%67,%68,%69,%70,%71}, da, db, 1, 1, 1, 1, %76;\n}\n"
    : "+f"(d[0]),"+f"(d[1]),"+f"(d[2]),"+f"(d[3]),"+f"(d[4]),"+f"(d[5]),"+f"(d[6]),"+f"(d[7]),"+f"(d[8]),"+f"(d[9]),"+f"(d[10]),"+f"(d[11]),"+f"(d[12]),"+f"(d[13]),"+f"(d[14]),"+f"(d[15]),"+f"(d[16]),"+f"(d[17]),"+f"(d[18]),"+f"(d[19]),"+f"(d[20]),"+f"(d[21]),"+f"(d[22]),"+f"(d[23]),"+f"(d[24]),"+f"(d[25]),"+f"(d[26]),"+f"(d[27]),"+f"(d[28]),"+f"(d[29]),"+f"(d[30]),"+f"(d[31]),"+f"(d[32]),"+f"(d[33]),"+f"(d[34]),"+f"(d[35]),"+f"(d[36]),"+f"(d[37]),"+f"(d[38]),"+f"(d[39]),"+f"(d[40]),"+f"(d[41]),"+f"(d[42]),"+f"(d[43]),"+f"(d[44]),"+f"(d[45]),"+f"(d[46]),"+f"(d[47]),"+f"(d[48]),"+f"(d[49]),"+f"(d[50]),"+f"(d[51]),"+f"(d[52]),"+f"(d[53]),"+f"(d[54]),"+f"(d[55]),"+f"(d[56]),"+f"(d[57]),"+f"(d[58]),"+f"(d[59]),"+f"(d[60]),"+f"(d[61]),"+f"(d[62]),"+f"(d[63]),"+f"(d[64]),"+f"(d[65]),"+f"(d[66]),"+f"(d[67]),"+f"(d[68]),"+f"(d[69]),"+f"(d[70]),"+f"(d[71])
    : "r"(al), "r"(ah), "r"(bl), "r"(bh), "n"(TB));
}
template<int TB> __device__ __forceinline__ void wgmma_ss_96_0(float (&d)[80], uint32_t al, uint32_t ah, uint32_t bl, uint32_t bh) {
  asm volatile("{\n.reg .b64 da, db;\nmov.b64 da, {%48, %49};\nmov.b64 db, {%50, %51};\n"
    "wgmma.mma_async.sync.aligned.m64n96k16.f32.bf16.bf16 {%0,%1,%2,%3,%4,%5,%6,%7,%8,%9,%10,%11,%12,%13,%14,%15,%16,%17,%18,%19,%20,%21,%22,%23,%24,%25,%26,%27,%28,%29,%30,%31,%32,%33,%34,%35,%36,%37,%38,%39,%40,%41,%42,%43,%44,%45,%46,%47}, da, db, 1, 1, 1, 1, %52;\n}\n"
    : "+f"(d[0]),"+f"(d[1]),"+f"(d[2]),"+f"(d[3]),"+f"(d[4]),"+f"(d[5]),"+f"(d[6]),"+f"(d[7]),"+f"(d[8]),"+f"(d[9]),"+f"(d[10]),"+f"(d[11]),"+f"(d[12]),"+f"(d[13]),"+f"(d[14]),"+f"(d[15]),"+f"(d[16]),"+f"(d[17]),"+f"(d[18]),"+f"(d[19]),"+f"(d[20]),"+f"(d[21]),"+f"(d[22]),"+f"(d[23]),"+f"(d[24]),"+f"(d[25]),"+f"(d[26]),"+f"(d[27]),"+f"(d[28]),"+f"(d[29]),"+f"(d[30]),"+f"(d[31]),"+f"(d[32]),"+f"(d[33]),"+f"(d[34]),"+f"(d[35]),"+f"(d[36]),"+f"(d[37]),"+f"(d[38]),"+f"(d[39]),"+f"(d[40]),"+f"(d[41]),"+f"(d[42]),"+f"(d[43]),"+f"(d[44]),"+f"(d[45]),"+f"(d[46]),"+f"(d[47])
    : "r"(al), "r"(ah), "r"(bl), "r"(bh), "n"(TB));
}
template<int TB> __device__ __forceinline__ void wgmma_ss_48_48(float (&d)[80], uint32_t al, uint32_t ah, uint32_t bl, uint32_t bh) {
  asm volatile("{\n.reg .b64 da, db;\nmov.b64 da, {%24, %25};\nmov.b64 db, {%26, %27};\n"
    "wgmma.mma_async.sync.aligned.m64n48k16.f32.bf16.bf16 {%0,%1,%2,%3,%4,%5,%6,%7,%8,%9,%10,%11,%12,%13,%14,%15,%16,%17,%18,%19,%20,%21,%22,%23}, da, db, 1, 1, 1, 1, %28;\n}\n"
    : "+f"(d[48]),"+f"(d[49]),"+f"(d[50]),"+f"(d[51]),"+f"(d[52]),"+f"(d[53]),"+f"(d[54]),"+f"(d[55]),"+f"(d[56]),"+f"(d[57]),"+f"(d[58]),"+f"(d[59]),"+f"(d[60]),"+f"(d[61]),"+f"(d[62]),"+f"(d[63]),"+f"(d[64]),"+f"(d[65]),"+f"(d[66]),"+f"(d[67]),"+f"(d[68]),"+f"(d[69]),"+f"(d[70]),"+f"(d[71])
    : "r"(al), "r"(ah), "r"(bl), "r"(bh), "n"(TB));
}
__device__ __forceinline__ void wgmma_rs_72(float (&d)[36], uint32_t a0, uint32_t a1, uint32_t a2, uint32_t a3, uint32_t bl, uint32_t bh, int sd) {
  asm volatile("{\n.reg .pred p;\n.reg .b64 db;\nsetp.ne.b32 p, %42, 0;\nmov.b64 db, {%40, %41};\n"
    "wgmma.mma_async.sync.aligned.m64n72k16.f32.bf16.bf16 {%0,%1,%2,%3,%4,%5,%6,%7,%8,%9,%10,%11,%12,%13,%14,%15,%16,%17,%18,%19,%20,%21,%22,%23,%24,%25,%26,%27,%28,%29,%30,%31,%32,%33,%34,%35}, {%36,%37,%38,%39}, db, p, 1, 1, 1;\n}\n"
    : "+f"(d[0]),"+f"(d[1]),"+f"(d[2]),"+f"(d[3]),"+f"(d[4]),"+f"(d[5]),"+f"(d[6]),"+f"(d[7]),"+f"(d[8]),"+f"(d[9]),"+f"(d[10]),"+f"(d[11]),"+f"(d[12]),"+f"(d[13]),"+f"(d[14]),"+f"(d[15]),"+f"(d[16]),"+f"(d[17]),"+f"(d[18]),"+f"(d[19]),"+f"(d[20]),"+f"(d[21]),"+f"(d[22]),"+f"(d[23]),"+f"(d[24]),"+f"(d[25]),"+f"(d[26]),"+f"(d[27]),"+f"(d[28]),"+f"(d[29]),"+f"(d[30]),"+f"(d[31]),"+f"(d[32]),"+f"(d[33]),"+f"(d[34]),"+f"(d[35])
    : "r"(a0), "r"(a1), "r"(a2), "r"(a3), "r"(bl), "r"(bh), "r"(sd));
}
__device__ __forceinline__ void wgmma_rs_48(float (&d)[24], uint32_t a0, uint32_t a1, uint32_t a2, uint32_t a3, uint32_t bl, uint32_t bh, int sd) {
  asm volatile("{\n.reg .pred p;\n.reg .b64 db;\nsetp.ne.b32 p, %30, 0;\nmov.b64 db, {%28, %29};\n"
    "wgmma.mma_async.sync.aligned.m64n48k16.f32.bf16.bf16 {%0,%1,%2,%3,%4,%5,%6,%7,%8,%9,%10,%11,%12,%13,%14,%15,%16,%17,%18,%19,%20,%21,%22,%23}, {%24,%25,%26,%27}, db, p, 1, 1, 1;\n}\n"
    : "+f"(d[0]),"+f"(d[1]),"+f"(d[2]),"+f"(d[3]),"+f"(d[4]),"+f"(d[5]),"+f"(d[6]),"+f"(d[7]),"+f"(d[8]),"+f"(d[9]),"+f"(d[10]),"+f"(d[11]),"+f"(d[12]),"+f"(d[13]),"+f"(d[14]),"+f"(d[15]),"+f"(d[16]),"+f"(d[17]),"+f"(d[18]),"+f"(d[19]),"+f"(d[20]),"+f"(d[21]),"+f"(d[22]),"+f"(d[23])
    : "r"(a0), "r"(a1), "r"(a2), "r"(a3), "r"(bl), "r"(bh), "r"(sd));
}
template<int N,int OFF,int TB> __device__ __forceinline__ void wgmma_ss(float (&d)[80], uint32_t al, uint32_t ah, uint32_t bl, uint32_t bh) {
  if constexpr (N==160) wgmma_ss_160_0<TB>(d, al, ah, bl, bh);
  else if constexpr (N==144) wgmma_ss_144_0<TB>(d, al, ah, bl, bh);
  else if constexpr (N==96) wgmma_ss_96_0<TB>(d, al, ah, bl, bh);
  else if constexpr (N==48) wgmma_ss_48_48<TB>(d, al, ah, bl, bh);
}

__device__ __forceinline__ void dft3(float2& a, float2& b, float2& c) {
  const float s = 0.86602540378443864676f;
  float2 t = make_float2(b.x + c.x, b.y + c.y), d = make_float2(b.x - c.x, b.y - c.y);
  float2 m = make_float2(fmaf(-0.5f, t.x, a.x), fmaf(-0.5f, t.y, a.y));
  a = make_float2(a.x + t.x, a.y + t.y);
  b = make_float2(fmaf(s, d.y, m.x), fmaf(-s, d.x, m.y));
  c = make_float2(fmaf(-s, d.y, m.x), fmaf(s, d.x, m.y));
}
__device__ __forceinline__ void dft9(float2 (&x)[9]) {
  const float2 w1 = make_float2(0.76604444311897803520f, -0.64278760968653932632f);
  const float2 w2 = make_float2(0.17364817766693034885f, -0.98480775301220805937f);
  const float2 w4 = make_float2(-0.93969262078590838405f, -0.34202014332566873304f);
  dft3(x[0], x[3], x[6]); dft3(x[1], x[4], x[7]); dft3(x[2], x[5], x[8]);
  x[4] = cmul(x[4], w1); x[7] = cmul(x[7], w2); x[5] = cmul(x[5], w2); x[8] = cmul(x[8], w4);
  dft3(x[0], x[1], x[2]); dft3(x[3], x[4], x[5]); dft3(x[6], x[7], x[8]);
  float2 t;
  t = x[1]; x[1] = x[3]; x[3] = t;
  t = x[2]; x[2] = x[6]; x[6] = t;
  t = x[5]; x[5] = x[7]; x[7] = t;
}

__device__ __forceinline__ uint32_t* mod_ptr(Scratch* sc, int u, int t128) {
  const int i = t128 & 15;
  return u < 72 ? sc->moda + (t128 >> 4) * (2 * D_) + 16 * u + 2 * (i & 7) + (i >> 3) : sc->mod + 16 * (u - 72) + i;
}
__device__ __forceinline__ void mod_unit(Scratch* sc, int u, int t128, uint32_t sw_, uint32_t bar, int ph, uint32_t rb, uint32_t tag) {
  const int w = t128 >> 5, l = t128 & 31;
  uint32_t b[18];
#pragma unroll
  for (int i = 0; i < 18; i++) b[i] = lds(red + 512 + (72 * w + 4 * i + (l & 3)) * 4);
  const uint32_t sa = pin(sw_ + (144 * w + (l & 7) + 8 * (l >> 4)) * 32 + (((l >> 3) ^ (l >> 2)) & 1) * 16);
  const uint32_t sr = pin(rb + (l >> 2) * 16 + w * 4);
  uint32_t* const dst = pin(mod_ptr(sc, u, t128));
  const int kind = u / 36;
  const float mul = __uint_as_float(pin(__float_as_uint(kind == 0 ? 16.0f : 1.0f))), add = __uint_as_float(pin(__float_as_uint(kind == 1 || kind == 4 ? 1.0f : 0.0f)));
  mbar_wait(bar, ph);
  if (t128 == 0 && u < 72) TS(10);
  float d[3][4];
#pragma unroll
  for (int i = 0; i < 9; i++) {
    uint32_t a0, a1, a2, a3;
    asm volatile("ldmatrix.sync.aligned.m8n8.x4.trans.shared.b16 {%0,%1,%2,%3}, [%4];" : "=r"(a0), "=r"(a1), "=r"(a2), "=r"(a3) : "r"(sa + i * 512) : "memory");
    if (i < 3) mma16<false>(d[i], a0, a1, a2, a3, b[2 * i], b[2 * i + 1]);
    else mma16<true>(d[i % 3], a0, a1, a2, a3, b[2 * i], b[2 * i + 1]);
  }
  if ((l & 3) == 0) { sts(sr, __float_as_uint(d[0][0] + d[1][0] + d[2][0])); sts(sr + 128, __float_as_uint(d[0][2] + d[1][2] + d[2][2])); }
  bar_sync(4, 128);
  const uint4 v = lds4(rb + (l & 15) * 16);
  const float m = rbf(fmaf(rbf((__uint_as_float(v.x) + __uint_as_float(v.y)) + (__uint_as_float(v.z) + __uint_as_float(v.w))), mul, add));
  if (u < 72 || t128 < 16) *dst = __float_as_uint(m) | tag;
}

__device__ __forceinline__ void ln_stats2(const float (&a)[18], const float (&b)[18], float sc, float& oa, float& ra, float& ob, float& rb) {
  float v[4] = {0.f, 0.f, 0.f, 0.f}, w[4] = {0.f, 0.f, 0.f, 0.f};
#pragma unroll
  for (int i = 0; i < 18; i += 2) {
    v[0] += a[i]; v[1] = fmaf(a[i], a[i], v[1]); v[2] += b[i]; v[3] = fmaf(b[i], b[i], v[3]);
    w[0] += a[i + 1]; w[1] = fmaf(a[i + 1], a[i + 1], w[1]); w[2] += b[i + 1]; w[3] = fmaf(b[i + 1], b[i + 1], w[3]);
  }
#pragma unroll
  for (int e = 0; e < 4; e++) v[e] += w[e];
#pragma unroll
  for (int o = 16; o; o >>= 1) {
#pragma unroll
    for (int e = 0; e < 4; e++) v[e] += __shfl_xor_sync(0xffffffffu, v[e], o);
  }
  const float ma = v[0] * (1.0f / D_), mb = v[2] * (1.0f / D_);
  ra = sc * rsqrtf(fmaxf(fmaf(-ma, ma, v[1] * (1.0f / D_)), 0.f) + 1e-5f);
  rb = sc * rsqrtf(fmaxf(fmaf(-mb, mb, v[3] * (1.0f / D_)), 0.f) + 1e-5f);
  oa = -ma * ra; ob = -mb * rb;
}

__device__ __forceinline__ float tmat(int c, int q, int j) {
  const int ph = q == 1 ? 1024 * j : (q >> 1) * (c + 128 * j) + 512 * (q & 1);
  return __cosf((float)(((ph + 1024) & 2047) - 1024) * (6.283185307179586f / 2048.0f));
}
__device__ __forceinline__ uint32_t line_off(int k1, int kap, int pi, int f) {
  int kd = 64 * k1 + 9 * kap;
  if (kap == 0 && k1 > 4) kd -= 288;
  if (kd >= D_) kd -= D_;
  return pi * 2400 + ((min(kd, D_ - kd) ^ f) << 3);
}

constexpr int JSK = 5;
struct Ring { uint32_t st, ph; };
template <bool G2, class T> __device__ __forceinline__ void ring_next(T& st, T& ph) {
  if (++st == NST) st = 0;
  ph ^= ((G2 ? 0xDu : 0x1u) >> st) & 1;
}
__device__ __forceinline__ void arrive_if(uint32_t a, uint32_t p) {
  asm volatile("{\n.reg .pred p;\nsetp.ne.u32 p, %1, 0;\n@p mbarrier.arrive.shared::cta.b64 _, [%0];\n}" ::"r"(a), "r"(p) : "memory");
}
template <int NA> __device__ __forceinline__ void reg_fence_n(float (&d)[80]) {
#pragma unroll
  for (int i = 0; i < NA; i++) asm volatile("" : "+f"(d[i])::"memory");
}
template <int MODE>
__device__ __forceinline__ void gemm_main(float (&acc)[80], uint32_t da0, uint32_t da1, uint32_t db0, uint32_t db1, int wg, Ring& rg,
                                          uint32_t* x1p, const uint32_t (&xr)[18]) {
  static_assert(JSK == NST - 1, "the held slot is the first one that is not refilled by GEMM1");
  constexpr int NKB = MODE == 3 ? 36 : 32;
  constexpr uint32_t HA = 0x40000040u, HB = MODE == 3 ? 0x40000040u : 0x80000020u;
  constexpr uint32_t KA = 2048 >> 4, KB = MODE == 3 ? (32 >> 4) : (1024 >> 4);
  constexpr int NA = MODE ? 72 : 80;
  const uint32_t t = threadIdx.x & 127;
  const uint32_t eb = full0 + 8 * NST;
  uint32_t pb = 0, rel = t == 0, prel = 0, ok = 0;
  int n = MODE == 3 ? NKB - JSK : X1K + 2 * wg;
#pragma unroll 1
  for (int pass = MODE == 3 ? 0 : -1;; pass++) {
#pragma unroll 1
    do {
      const uint32_t so = rg.st * (STAGE >> 4), cb = eb + 8 * rg.st;
      if (__builtin_expect(!ok, 0)) mbar_wait(full0 + 8 * rg.st, rg.ph);
      reg_fence_n<NA>(acc);
      wg_fence();
#pragma unroll
      for (int k = 0; k < 4; k++) {
        if (k == 3) { ring_next<MODE == 3>(rg.st, rg.ph); ok = PEEK ? mbar_test(full0 + 8 * rg.st, rg.ph) : 0; }
        if (MODE == 0) wgmma_ss<160, 0, 1>(acc, da0 + so + k * KA, HA, db0 + so + k * KB, HB);
        else if (MODE == 3) wgmma_ss<144, 0, 0>(acc, da0 + so + k * KA, HA, db0 + so + k * KB, HB);
        else {
          wgmma_ss<96, 0, 1>(acc, da0 + so + k * KA, HA, db0 + so + k * KB, HB);
          wgmma_ss<48, 48, 1>(acc, da1 + so + k * KA, HA, db1 + so + k * KB, HB);
        }
      }
      wg_commit();
      wg_wait<1>();
      reg_fence_n<NA>(acc);
      arrive_if(pb, prel);
      pb = cb; prel = rel;
    } while (--n);
    if (pass == 2 - wg) break;
    if (MODE != 3 && pass < 0) {
      if (blockIdx.x < 128) {
#pragma unroll
        for (int i = 0; i < 9; i++) { x1p[32 * i] = xr[i]; x1p[128 * 288 + 32 * i] = xr[9 + i]; }
      }
      n = NKB - JSK - X1K - 2 * wg;
      continue;
    }
    n = 1;
    if (pass == 0) {
      if (MODE != 3) prel = rel & wg;
      else rel = 0;
      n = JSK - 1 + wg;
      if (!wg) continue;
      wg_wait<0>();
      arrive_if(pb, prel);
      prel = 0;
    }
    bar_sync(1, 256);
  }
  wg_wait<0>();
  reg_fence_n<NA>(acc);
  if (MODE != 3) arrive_if(pb, prel & ~wg);
}

__device__ __forceinline__ float gelu_arg(float h) { return h * fmaf(8.0f * 0.044715f * 0.7978845608028654f, h * h, 2.0f * 0.7978845608028654f); }

__device__ __forceinline__ int kb2_order(int i) { const int wv = i / 6; return 6 * (i - 6 * wv) + ((0x431250 >> (4 * wv)) & 7); }

__device__ __forceinline__ void wait_flags(const unsigned* base, int n, int idx, unsigned target, uint64_t& ready) {
  if ((ready >> idx) & 1) return;
  const int l = threadIdx.x & 31;
  int it = 0;
  while (true) {
    unsigned a = ld_rlx(base + l), b = l + 32 < n ? ld_rlx(base + l + 32) : target;
    ready = (uint64_t)__ballot_sync(0xffffffffu, (int)(a - target) >= 0) | ((uint64_t)__ballot_sync(0xffffffffu, (int)(b - target) >= 0) << 32);
    if (((ready >> idx) & 1) || ++it > SPIN_MAX) break;
  }
  fence_async_glb();
}

enum { B_FULL = 0, B_EMPTY = 6, B_FLT = 12, B_Z1, B_Z2, B_GO, B_S4, B_S5, B_WM, B_NUM, B_W0 = B_NUM };

__global__ void __launch_bounds__(NTHR, 1)
fused_kernel(const Params p, const __grid_constant__ Maps maps) {
  extern __shared__ __align__(1024) uint8_t smem_raw[];
  const int tid = threadIdx.x, cta = blockIdx.x, t128 = tid & 127;
  const int wp = __shfl_sync(0xffffffffu, tid >> 5, 0), wg = wp >> 2;
  const int l = tid & 31, g = l >> 2, t = l & 3;
  Scratch* const sc = p.s;
  const bool rows = cta < 128;
  const int R = cta - 12;

  uint32_t xr[18];
  uint32_t cv[3];
  const unsigned ep = ld_rlx(&sc->cnt[C_EP]) + 1;
  if (tid == 0) TS(0);
  if (wg == 2) {
#pragma unroll
    for (int i = 0; i < 3; i++) cv[i] = ld_nc(reinterpret_cast<const uint32_t*>(p.c) + min(t128 + 128 * i, 287));
    if (wp == 9 && l < 9 && rows) {
      const int h = 9 * cta + l;
      prefetch_l2(reinterpret_cast<const uint8_t*>(p.wmod) + (size_t)(h >> 1) * (12 * D_) + (h & 1) * (2 * D_), 2 * D_);
    }
    if (tid == 256 && cta < 72) {
      mbar_init(full0 + 8 * B_W0, 1);
      fence_async_smem();
      mbar_expect(full0 + 8 * B_W0, 18432);
#pragma unroll 1
      for (int i = 0; i < 3; i++) tma2d(sbase + O_P2 + i * 6144, &maps.wm, 16 * cta, 192 * i, full0 + 8 * B_W0);
    }
    __syncwarp();
#pragma unroll 1
    for (int u = cta < 72 ? cta : 72 + cta; u < 216; u += u < 72 ? 72 : NCTA) if (u < 72 || t128 < 16) *mod_ptr(sc, u, t128) = 0;
    if (wp == 11 && smem_u32(smem_raw) != sbase) __trap();
    if (wp >= 10 && elect()) {
#pragma unroll 1
      for (int i = wp - 10; i < B_NUM; i += 2) mbar_init(full0 + 8 * i, i == B_FLT ? 4 : i == B_WM ? 3 : (i >= B_EMPTY && i < B_FLT) || i == B_S4 || i == B_S5 ? 2 : 1);
      fence_async_smem();
    }
    __syncwarp();
  }
  CK(0);
  auto load_x = [&]() {
    const uint32_t* xs = reinterpret_cast<const uint32_t*>(p.x) + (size_t)(cta + 256 * wp) * 288 + l;
#pragma unroll
    for (int i = 0; i < 9; i++) { xr[i] = ld_nc(xs + 32 * i); xr[9 + i] = ld_nc(xs + 128 * 288 + 32 * i); }
  };
  if (rows && wg < 2) load_x();
  if (tid == 64 && cta == NCTA - 1) prefetch_l2(p.tab, sizeof(T_TAB));
  __syncwarp();
  const uint32_t tag16 = (ep & 0x7fffu) | 0x8000u, tag1 = ep & 1u;

  if (wg == 2) {
#pragma unroll
    for (int i = 0; i < 3; i++) {
      const float c0 = bf_lo(cv[i]), c1 = bf_hi(cv[i]);
      sts(red + 512 + min(t128 + 128 * i, 287) * 4, pack_bf16(__fdividef(c0, 1.0f + __expf(-c0)), __fdividef(c1, 1.0f + __expf(-c1))));
    }
    if (wp == 9 && l < 14) asm volatile("prefetch.tensormap [%0];" ::"l"(&maps.z1 + l) : "memory");
    bar_sync(4, 128);
    if (cta < 72) {
      mod_unit(sc, cta, t128, sbase + O_P2, full0 + 8 * B_W0, 0, red, tag16);
      if (t128 == 0) TS(25);
    }
    CK(1);
  }
  const int pi = R / 15, col0 = 20 * (R - 15 * pi);
  const int xu = DF_ * pi + col0, xv = DF_ * (pi ? 16 - pi : 8) + col0;
  auto load_filter = [&](int a) {
    const int x = (a & 1) ? xv : xu;
    const bool wide = (x & 15) > 12;
    mbar_expect(full0 + 8 * B_FLT, wide ? 12288 : 8192);
    tma2d(sbase + O_RAW + a * 12288, &maps.wf[a & 2], x & ~15, 0, full0 + 8 * B_FLT);
    if (wide) tma2d(sbase + O_RAW + a * 12288 + 8192, &maps.wf[(a & 2) + 1], (x & ~15) + 32, 0, full0 + 8 * B_FLT);
  };
  const int kap = 8 * ((wp & 3) ^ (wg & 1)) + g;
  uint4 af[4];
  if (rows) {
    uint32_t tb[4];
#pragma unroll
    for (int i = 0; i < 4; i++) tb[i] = pack_bf16(tmat(cta, 8 * (i >> 1) + g, 2 * t + 8 * (i & 1)), tmat(cta, 8 * (i >> 1) + g, 2 * t + 8 * (i & 1) + 1));
    uint32_t sb1[3], lo[9];
#pragma unroll
    for (int i = 0; i < 4; i++) tb[i] = pin(tb[i]);
#pragma unroll
    for (int i = 0; i < 3; i++) {
      const int d = 48 * wp + 16 * i + (l & 15);
      sb1[i] = pin(sbase + O_B1 + (l >> 4) * 9216 + (d % 9) * 1024 + (d & 63) * 16);
    }
    const uint32_t snt = pin(sbase + O_NRM + ((l & 7) + 8 * (l >> 4)) * 1168 + (48 * wp + (l & 8)) * 2);
    uint2 ms[3], mc[3];
    const uint32_t smask = pin(t ? 0u : 0xffff0000u);
    const uint32_t* const mp = pin(sc->moda + (cta >> 4) * (2 * D_) + 48 * wp + 2 * g);
    auto load_mod = [&]() {
#pragma unroll
      for (int i = 0; i < 3; i++) { ms[i] = ld_rlx2(mp + 16 * i); mc[i] = ld_rlx2(mp + D_ + 16 * i); }
    };
    if (wg < 2) {
#pragma unroll
      for (int k1 = 0; k1 < 9; k1++) lo[k1] = pin(sbase + O_Z1 + line_off(k1, kap, 4 * wg + t, cta & 3));
      float a[18], b[18];
#pragma unroll
      for (int i = 0; i < 9; i++) { a[2 * i] = bf_lo(xr[i]); a[2 * i + 1] = bf_hi(xr[i]); b[2 * i] = bf_lo(xr[9 + i]); b[2 * i + 1] = bf_hi(xr[9 + i]); }
      float oa, ra, ob, rb;
      ln_stats2(a, b, 1.0f, oa, ra, ob, rb);
      CK(1);
      const uint32_t sn = sbase + O_NRM + wp * 2336 + l * 4;
#pragma unroll
      for (int i = 0; i < 9; i++) {
        sts(sn + i * 128, pack_bf16(fmaf(a[2 * i], ra, oa), fmaf(a[2 * i + 1], ra, oa)));
        sts(sn + 1168 + i * 128, pack_bf16(fmaf(b[2 * i], rb, ob), fmaf(b[2 * i + 1], rb, ob)));
      }
      CK(2);
      bar_arrive(10, NTHR);
      load_mod();
#pragma unroll
      for (int kk = 0; kk < 4; kk++) af[kk] = ld_nc4(p.tab + TB_F + kk * 128 + (t128 ^ (wg << 5)));
      bar_sync(1, 256);
      if (tid == 0) TS(2);
    } else {
      bar_sync(10, NTHR);
      load_mod();
      CK(2);
      if (PFF && wp >= 12 - PFF && elect()) prefetch_l2(reinterpret_cast<const uint8_t*>(wp == 10 ? p.wr : p.wi) + cta * 9248, 9248);
      __syncwarp();
    }
    float rs[3][8];
#pragma unroll
    for (int i = 0; i < 3; i++) {
      uint32_t a0, a1, a2, a3;
      asm volatile("ldmatrix.sync.aligned.m8n8.x4.trans.shared.b16 {%0,%1,%2,%3}, [%4];" : "=r"(a0), "=r"(a1), "=r"(a2), "=r"(a3)
                   : "r"(snt + 32 * i) : "memory");
      mma16<false>(&rs[i][0], a0, a1, a2, a3, tb[0], tb[1]);
      mma16<false>(&rs[i][4], a0, a1, a2, a3, tb[2], tb[3]);
    }
    CK(3);
    {
      int it = 0;
#pragma unroll 1
      while (true) {
        uint32_t bad = 0;
#pragma unroll
        for (int i = 0; i < 3; i++) bad |= diff2(ms[i].x, ms[i].y, tag16) | diff2(mc[i].x, mc[i].y, tag16);
        if (!any(bad & 0xffffu) || ++it > SPIN_MAX) break;
        load_mod();
      }
      CK(4);
      if (tid == 0) TS(3);
#pragma unroll
      for (int i = 0; i < 3; i++) {
        const float c0 = bf_hi(mc[i].x), c1 = bf_hi(mc[i].y);
        const float s0 = __uint_as_float(ms[i].x & smask), s1 = __uint_as_float(ms[i].y & smask);
        stmatrix4(sb1[i], pack_bf16(fmaf(rs[i][0], c0, s0), rs[i][1] * c0), pack_bf16(fmaf(rs[i][2], c1, s1), rs[i][3] * c1),
                  pack_bf16(rs[i][4] * c0, rs[i][5] * c0), pack_bf16(rs[i][6] * c1, rs[i][7] * c1));
      }
    }
    fence_async_smem();
    CK(5);
    if (wg == 2) {
      bar_arrive(5, NTHR);
      if (R >= 0 && elect()) load_filter(wp - 8);
      __syncwarp();
    } else {
      bar_sync(5, NTHR);
      CK(6);
      float acc[36];
      const uint32_t db = (((sbase + O_B1 + wg * 9216) & 0x3FFFF) >> 4) | ((128 >> 4) << 16);
      wg_fence();
#pragma unroll
      for (int kk = 0; kk < 4; kk++) wgmma_rs_72(acc, af[kk].x, af[kk].y, af[kk].z, af[kk].w, db + kk * 16, 1024 >> 4, kk);
      wg_commit();
      wg_wait<0>();
      reg_fence(acc);
      CK(7);
      float2 za[9], zb[9];
#pragma unroll
      for (int i = 0; i < 9; i++) { za[i] = make_float2(acc[4 * i], acc[4 * i + 2]); zb[i] = make_float2(acc[4 * i + 1], acc[4 * i + 3]); }
      dft9(za); dft9(zb);
      if (kap == 0) {
#pragma unroll
        for (int k = 1; k < 5; k++) {
          float2 a = za[k], b = za[9 - k];
          za[k] = make_float2(a.x + b.x, a.y - b.y); za[9 - k] = make_float2(a.y + b.y, b.x - a.x);
          a = zb[k]; b = zb[9 - k];
          zb[k] = make_float2(a.x + b.x, a.y - b.y); zb[9 - k] = make_float2(a.y + b.y, b.x - a.x);
        }
        sts2(lo[0] + 288 * 8, set_tag(pack_bf16(za[0].y, 0.f), tag1), pack_bf16(zb[0].y, 0.f));
        za[0].y = 0.f; zb[0].y = 0.f;
      }
      __syncwarp();
#pragma unroll
      for (int k1 = 0; k1 < 9; k1++) sts2(lo[k1], set_tag(pack_bf16(za[k1].x, za[k1].y), tag1), pack_bf16(zb[k1].x, zb[k1].y));
      fence_async_smem();
      CK(8);
      bar_arrive(2 + wg, 160);
    }
  } else {
    __syncthreads();
  }

  if ((wp >> 1) == 4) {
    if (rows) {
      const int slot = 4 * (cta & 7) + ((cta >> 4) & 3) + 32 * (2 * (cta >> 6) + ((cta >> 3) & 1));
      const uint32_t c0 = upin(40 * slot), c1 = upin(60 * (wp - 8)), src = upin(sbase + O_Z1 + (wp - 8) * 9600);
      const CUtensorMap* mp = upin(&maps.z1);
      unsigned* hint = pin(&sc->cnt[C_Z1 + 32 * (wp - 8)]);
      bar_sync(wp - 6, 160);
      if (elect()) {
        tma_st2d(mp, src, c0, c1);
        HW();
        red_add(hint, 1);
        if (wp == 8) TS(4);
      }
    } else {
      int it = 0;
      while (any((ld_rlx(sc->moda + 36 * l) ^ tag16) & 0xffffu) && ++it < SPIN_MAX) {}
      if (elect()) { load_filter(wp - 8); load_filter(wp - 6); }
    }
    __syncwarp();
  }
  auto load_wm = [&](int u) {
    if (wp > 8 && elect()) {
      mbar_expect(full0 + 8 * B_WM, 6144);
      tma2d(sbase + O_NRM + (wp - 9) * 6144, &maps.wm, 16 * u, 192 * (wp - 9), full0 + 8 * B_WM);
    }
    __syncwarp();
  };
  if (R >= 0) {
    const int nl = (col0 + wp < DF_) + (wg < 2 && col0 + wp + 12 < DF_);
    uint4 cf[2][4], G[4];
#pragma unroll
    for (int i = 0; i < 4; i++) {
      cf[0][i] = __ldg(p.tab + TB_P2 + i * 32 + l);
      cf[1][i] = __ldg(p.tab + TB_P2 + (pi ? i : 4 + i) * 32 + l);
      G[i] = __ldg(p.tab + TB_P2 + (8 + i) * 32 + l);
    }
    const uint32_t* zin = sc->z1 + (size_t)R * 5120;
    if (wp == 10) {
      const uint32_t* zu = upin(zin);
      if (elect()) mbar_expect(full0 + 8 * B_Z1, 20480);
      wait_cnt(&sc->cnt[C_Z1 + 32 * (pi >> 2)], 128 * ep);
      if (elect()) {
        bulk_ld(sbase + O_P2, zu, 20480, full0 + 8 * B_Z1);
        TS(12);
      }
      __syncwarp();
    }
    mbar_wait(full0 + 8 * B_FLT, 0);
    CK(9);
    float wn[16], wc[16];
#pragma unroll 1
    for (int ln = nl - 1; ln >= 0; ln--) {
      const int col = col0 + wp + 12 * ln, k2 = (57 * col) & 63;
      const bool cj = k2 > 32 || (k2 == 32 && col != 288);
      const float nr = ((col & 31) == 0 && col != 0 && col != 288 ? 0.5f : 1.0f) / ((float)S_ * D_), ni = cj ? -nr : nr;
#pragma unroll
      for (int i = 0; i < 16; i++) wn[i] = wc[i];
#pragma unroll
      for (int cl = 0; cl < 2; cl++) {
        const int v = cl ^ (cj && pi), e = ((v ? xv : xu) & 15) + wp + 12 * ln, sh = e < 32 ? 6 : 5;
        const uint32_t base = sbase + O_RAW + v * 12288 + (e < 32 ? 2 * e : 8192 - 64 + 2 * e), msk = e < 32 ? 0x30 : 0x10;
        const int dm = v ? (cj || pi ? -1 : 0) : 0;
#pragma unroll
        for (int tt = 0; tt < 4; tt++) {
          const int kc = g + 64 * (tt >> 1) + 16 * t + 8 * (tt & 1);
          uint32_t a = base + ((((cj ? -kc : kc) + dm) & 127) << sh);
          a ^= (a >> 3) & msk;
          wc[4 * tt + 2 * cl] = lds_bf(a) * nr; wc[4 * tt + 2 * cl + 1] = lds_bf(a + 24576) * ni;
        }
      }
    }
    const float al = pi ? 1.0f : 0.0f;
    CK(10);
    uint32_t off = pin(l * 160 + ((wp ^ (g & 3)) << 3));
    uint32_t offo = pin(sbase + O_P2 + 20480 + off - 64 * l), po = 3072;
    unsigned* hz2 = pin(&sc->cnt[C_Z2]);
    mbar_wait(full0 + 8 * B_Z1, 0);
    CK(11);
    if (tid == 0) TS(8);
    if (wg == 2) load_wm(72 + cta);
#pragma unroll 1
    for (int ln = 0; ln < 2; ln++, off += 96, offo += 12288 - 32 * l, po = 2048) {
      if (ln < nl) {
      uint2 v[4];
#pragma unroll
      for (int i = 0; i < 4; i++) v[i] = lds2(sbase + O_P2 + off + i * 5120);
      if (__builtin_expect(any((diff2(v[0].x, v[1].x, tag1) | diff2(v[2].x, v[3].x, tag1)) & 1), 0)) {
        FAILCNT(0);
        int it = 0;
        do {
#pragma unroll
          for (int i = 0; i < 4; i++) v[i] = ld_rlx2(reinterpret_cast<const uint8_t*>(zin) + off + i * 5120);
        } while (any((diff2(v[0].x, v[1].x, tag1) | diff2(v[2].x, v[3].x, tag1)) & 1) && ++it < SPIN_MAX);
      }
      float d[4][4];
      uint32_t A[8];
#pragma unroll
      for (int h = 0; h < 2; h++) {
        mma16<false>(d[2 * h], cf[0][0].x, cf[0][0].y, cf[0][0].z, cf[0][0].w, v[h].x, v[2 + h].x);
        mma16<false>(d[2 * h + 1], cf[1][0].x, cf[1][0].y, cf[1][0].z, cf[1][0].w, v[h].y, v[2 + h].y);
      }
#pragma unroll
      for (int h = 0; h < 2; h++)
#pragma unroll
        for (int L = 0; L < 2; L++) {
          const uint4 tw = cf[L][2 + h];
          const float* z = d[2 * h + L];
          const float2 z0 = cmul(make_float2(z[0], z[2]), make_float2(__uint_as_float(tw.x), __uint_as_float(tw.y)));
          const float2 z1 = cmul(make_float2(z[1], z[3]), make_float2(__uint_as_float(tw.z), __uint_as_float(tw.w)));
          A[4 * h + L] = pack_bf16(z0.x, z0.y); A[4 * h + 2 + L] = pack_bf16(z1.x, z1.y);
        }
#pragma unroll
      for (int tt = 0; tt < 4; tt++) {
        mma16<false>(d[tt], A[0], A[1], A[2], A[3], G[tt].x, G[tt].y);
        mma16<true>(d[tt], A[4], A[5], A[6], A[7], G[tt].z, G[tt].w);
      }
#pragma unroll
      for (int tt = 0; tt < 4; tt++) {
        const float ar = d[tt][0], aj = d[tt][1], br = d[tt][2], bj = d[tt][3];
        const float2 y1 = cmul(make_float2(fmaf(-al, bj, ar), fmaf(al, br, aj)), make_float2(wc[4 * tt], wc[4 * tt + 1]));
        const float2 y2 = cmul(make_float2(fmaf(al, ar, bj), fmaf(al, aj, -br)), make_float2(wc[4 * tt + 2], wc[4 * tt + 3]));
        A[2 * tt] = pack_bf16(fmaf(al, y2.x, y1.x), fmaf(-al, y2.y, -y1.y));
        A[2 * tt + 1] = pack_bf16(fmaf(al, y1.y, -y2.y), fmaf(al, y1.x, -y2.x));
      }
#pragma unroll
      for (int i = 0; i < 16; i++) wc[i] = wn[i];
#pragma unroll
      for (int tt = 0; tt < 4; tt++) {
        mma16<false>(d[tt], A[0], A[1], A[2], A[3], G[tt].x, G[tt].y);
        mma16<true>(d[tt], A[4], A[5], A[6], A[7], G[tt].z, G[tt].w);
      }
#pragma unroll
      for (int h = 0; h < 2; h++)
#pragma unroll
        for (int L = 0; L < 2; L++) {
          const uint4 tw = cf[L][2 + h];
          const float2 z0 = cmul(make_float2(d[2 * h][2 * L], d[2 * h][2 * L + 1]), make_float2(__uint_as_float(tw.x), __uint_as_float(tw.y)));
          const float2 z1 = cmul(make_float2(d[2 * h + 1][2 * L], d[2 * h + 1][2 * L + 1]), make_float2(__uint_as_float(tw.z), __uint_as_float(tw.w)));
          A[4 * h + 2 * L] = movm(pack_bf16(z0.x, z1.x)); A[4 * h + 2 * L + 1] = movm(pack_bf16(z0.y, z1.y));
        }
#pragma unroll
      for (int h = 0; h < 2; h++) {
        mma16<false>(d[0], cf[0][1].x, cf[0][1].y, cf[0][1].z, cf[0][1].w, A[4 * h], A[4 * h + 1]);
        mma16<false>(d[1], cf[1][1].x, cf[1][1].y, cf[1][1].z, cf[1][1].w, A[4 * h + 2], A[4 * h + 3]);
#pragma unroll
        for (int e = 0; e < 2; e++)
          sts2(offo + (2 * h + e) * po, set_tag(pack_bf16(d[0][e], d[0][2 + e]), tag1), pack_bf16(d[1][e], d[1][2 + e]));
      }
      fence_async_smem();
      }
      CK(12 + ln);
      if (wp != 8 - 8 * ln) bar_arrive(ln ? 6 : 15, ln ? 256 : NTHR);
      else {
        bar_sync(ln ? 6 : 15, ln ? 256 : NTHR);
        if (elect()) {
          tma_st2d(&maps.z2[ln], sbase + O_P2 + 20480 + ln * 12288, 40 * R + 24 * ln, 0);
          HW();
          if (ln) { red_add(hz2, 1); TS(9); }
        }
        __syncwarp();
      }
      if (wg == 2) break;
    }
  }
  if (wg == 2) {
#pragma unroll 1
    for (int u = 72 + cta, k = 0; u < 216; u += NCTA, k ^= 1) {
      if (R < 0) { fence_async_smem(); bar_sync(4, 128); load_wm(u); }
      mod_unit(sc, u, t128, sbase + O_NRM, full0 + 8 * B_WM, k, red + 256 - 256 * k, tag16);
    }
    fence_async_smem();
    CK(13);
  }

  const int grp = cta / 11, m1 = cta - 11 * grp;
  const bool helper = (m1 & 3) == 3;
  const int f1 = 384 * grp + (helper ? 192 : 128) * (m1 >> 2);
  const int d1 = 160 * (m1 & 3), flip = m1 >= 7;
  const int a1bytes = helper ? 24576 : 16384;
  auto load_a1 = [&](int st, int kb) {
    mbar_expect(full0 + 8 * st, STAGE);
    tma4d_ef(sbase + st * STAGE, helper ? &maps.w1b : &maps.w1a, 4 * (kb >> 3), 16 * (kb & 7), f1 >> 6, full0 + 8 * st);
  };

  if (rows) {
#pragma unroll
    for (int kk = 0; kk < 4; kk++) af[kk] = __ldg(p.tab + TB_E + kk * 128 + t128);
    uint32_t tb[4], sy[6];
#pragma unroll
    for (int i = 0; i < 4; i++) tb[i] = pack_bf16(tmat(cta, 2 * t + 8 * (i & 1), 8 * (i >> 1) + g), tmat(cta, 2 * t + 8 * (i & 1) + 1, 8 * (i >> 1) + g));
#pragma unroll
    for (int i = 0; i < 6; i++) {
      const int rr = 16 * (wp & 3) + g + 8 * (i & 1);
      sy[i] = pin(sbase + O_Y + (t * 584 + 64 * ((3 * wg + (i >> 1) + 63 - rr) % 9) + rr) * 4);
    }
#pragma unroll
    for (int i = 0; i < 4; i++) tb[i] = pin(tb[i]);
    const int slot = 4 * (cta >> 4) + ((cta >> 1) & 3) + 32 * (2 * ((cta >> 3) & 1) + (cta & 1));
    const uint32_t* zin = sc->z2 + (size_t)slot * 4800;
    if (wg == 2) {
      {
        uint4 v[4];
        const int i3 = min(t128 + 384, 431);
        int it = 0;
        while (true) {
          uint32_t bad = 0;
#pragma unroll
          for (int k = 0; k < 4; k++) v[k] = ld_rlx4(sc->mod + 4 * (k < 3 ? t128 + 128 * k : i3));
#pragma unroll
          for (int k = 0; k < 4; k++) {
            v[k].x ^= tag16; v[k].y ^= tag16; v[k].z ^= tag16; v[k].w ^= tag16;
            bad |= v[k].x | v[k].y | v[k].z | v[k].w;
          }
          if (!any(bad & 0xffffu) || ++it > SPIN_MAX) break;
        }
#pragma unroll
        for (int k = 0; k < 4; k++) sts4(sbase + O_MOD + 16 * (k < 3 ? t128 + 128 * k : i3), v[k].x, v[k].y, v[k].z, v[k].w);
      }
      CK(14);
      mbar_wait(full0 + 8 * B_Z2, 0);
      if (elect()) {
        load_a1(wp - 8, wp - 8);
        if (wp > 8 && wp - 8 < NG1) prefetch_l2(reinterpret_cast<const uint8_t*>(p.w1) + (size_t)(128 * (4 * ((wp - 8) >> 1) + (cta >> 5)) + 64 * (wp & 1) + 2 * (cta & 31)) * (2 * F_), 4 * F_);
      }
      __syncwarp();
    } else {
      uint32_t lo[9];
#pragma unroll
      for (int k1 = 0; k1 < 9; k1++) lo[k1] = pin(sbase + O_IN + line_off(k1, kap, 4 * wg + t, (cta >> 4) & 3));
      const uint32_t lx = pin(lo[0] + (kap ? 0 : 288 * 8));
      const uint32_t sb3 = pin(sbase + O_B3 + wg * 1024 + (l >> 4) * 2048 + (2 * (kap & 24) + (l & 15)) * 16);
      CK(14);
      if (wp == 1) {
        const uint32_t* zu = upin(zin);
        if (elect()) mbar_expect(full0 + 8 * B_Z2, 19200);
        wait_cnt(&sc->cnt[C_Z2], 120 * ep);
        if (elect()) {
          bulk_ld(sbase + O_IN, zu, 19200, full0 + 8 * B_Z2);
          TS(14);
        }
        __syncwarp();
      }
      mbar_wait(full0 + 8 * B_Z2, 0);
      CK(15);
      if (tid == 0) TS(11);
      uint2 v[10];
      uint32_t bad = 0;
#pragma unroll
      for (int k1 = 0; k1 < 10; k1++) v[k1] = lds2(k1 < 9 ? lo[k1] : lx);
#pragma unroll
      for (int k1 = 0; k1 < 10; k1 += 2) bad |= diff2(v[k1].x, v[k1 + 1].x, tag1);
      if (__builtin_expect(any(bad & 1), 0)) {
        FAILCNT(1);
        int it = 0;
        do {
          bad = 0;
#pragma unroll
          for (int k1 = 0; k1 < 10; k1++) v[k1] = ld_rlx2(reinterpret_cast<const uint8_t*>(zin) + ((k1 < 9 ? lo[k1] : lx) - (sbase + O_IN)));
#pragma unroll
          for (int k1 = 0; k1 < 10; k1 += 2) bad |= diff2(v[k1].x, v[k1 + 1].x, tag1);
        } while (any(bad & 1) && ++it < SPIN_MAX);
      }
      float2 za[9], zb[9];
#pragma unroll
      for (int i = 0; i < 9; i++) { za[i] = make_float2(bf_lo(v[i].x), bf_hi(v[i].x)); zb[i] = make_float2(bf_lo(v[i].y), bf_hi(v[i].y)); }
      if (kap == 0) {
#pragma unroll
        for (int k = 1; k < 5; k++) {
          float2 a = za[k], b = za[9 - k];
          za[k] = make_float2(a.x - b.y, a.y + b.x); za[9 - k] = make_float2(a.x + b.y, b.x - a.y);
          a = zb[k]; b = zb[9 - k];
          zb[k] = make_float2(a.x - b.y, a.y + b.x); zb[9 - k] = make_float2(a.x + b.y, b.x - a.y);
        }
        za[0].y = bf_lo(v[9].x); zb[0].y = bf_lo(v[9].y);
      }
      __syncwarp();
      dft9(za); dft9(zb);
#pragma unroll
      for (int n = 0; n < 8; n += 2) {
        const int i0 = (9 - n) % 9, i1 = 8 - n;
        stmatrix4(sb3 + n * 2048, pack_bf16(za[i0].x, zb[i0].x), pack_bf16(za[i0].y, zb[i0].y), pack_bf16(za[i1].x, zb[i1].x), pack_bf16(za[i1].y, zb[i1].y));
      }
      stmatrix2(sb3 + 8 * 2048, pack_bf16(za[1].x, zb[1].x), pack_bf16(za[1].y, zb[1].y));
      fence_async_smem();
    }
    CK(16);
    __syncthreads();
    CK(17);
    float acc[24];
    const uint32_t db = (((sbase + O_B3 + wg * 6144) & 0x3FFFF) >> 4) | ((128 >> 4) << 16);
    wg_fence();
#pragma unroll
    for (int kk = 0; kk < 4; kk++) wgmma_rs_48(acc, af[kk].x, af[kk].y, af[kk].z, af[kk].w, db + kk * 16, 1024 >> 4, kk);
    wg_commit();
    uint32_t ga[9];
    uint2 sh[9], sw[9];
    if (wg < 2) {
#pragma unroll
      for (int i = 0; i < 9; i++) {
        const uint2 v = lds2(sbase + O_MOD + (64 * i + 2 * l) * 4);
        ga[i] = __byte_perm(v.x, v.y, 0x7632);
        sh[i] = lds2(sbase + O_MOD + (D_ + 64 * i + 2 * l) * 4);
        sw[i] = lds2(sbase + O_MOD + (2 * D_ + 64 * i + 2 * l) * 4);
      }
    }
    wg_wait<0>();
    reg_fence(acc);
    CK(18);
#pragma unroll
    for (int i = 0; i < 3; i++) {
      const float* a = &acc[8 * i];
      const uint32_t a0 = pack_bf16(a[0], a[1]), a1 = pack_bf16(a[2], a[3]), a2 = pack_bf16(a[4], a[5]), a3 = pack_bf16(a[6], a[7]);
#pragma unroll
      for (int jh = 0; jh < 2; jh++) {
        float y[4];
        mma16<false>(y, a0, a1, a2, a3, tb[2 * jh], tb[2 * jh + 1]);
        sts(sy[2 * i] + jh * (4 * 584 * 4), pack_bf16(y[0], y[1]));
        sts(sy[2 * i + 1] + jh * (4 * 584 * 4), pack_bf16(y[2], y[3]));
      }
    }
    CK(19);
    if (wg == 2) bar_arrive(7, NTHR);
    else {
      bar_sync(7, NTHR);
      CK(20);
      float a[18], b[18];
#pragma unroll
      for (int i = 0; i < 9; i++) {
        const uint2 y = lds2(sbase + O_Y + (wp * 584 + 64 * i + 2 * l) * 4);
        xr[i] = hfma2(ga[i], __byte_perm(y.x, y.y, 0x5410), xr[i]);
        xr[9 + i] = hfma2(ga[i], __byte_perm(y.x, y.y, 0x7632), xr[9 + i]);
        a[2 * i] = bf_lo(xr[i]); a[2 * i + 1] = bf_hi(xr[i]); b[2 * i] = bf_lo(xr[9 + i]); b[2 * i + 1] = bf_hi(xr[9 + i]);
      }
      float oa, ra, ob, rb;
      ln_stats2(a, b, 1.0f, oa, ra, ob, rb);
      CK(21);
#pragma unroll
      for (int i = 0; i < 9; i++) {
        const float c0 = __uint_as_float(sw[i].x), c1 = __uint_as_float(sw[i].y), s0 = __uint_as_float(sh[i].x), s1 = __uint_as_float(sh[i].y);
        a[2 * i] = fmaf(fmaf(a[2 * i], ra, oa), c0, s0); a[2 * i + 1] = fmaf(fmaf(a[2 * i + 1], ra, oa), c1, s1);
        b[2 * i] = fmaf(fmaf(b[2 * i], rb, ob), c0, s0); b[2 * i + 1] = fmaf(fmaf(b[2 * i + 1], rb, ob), c1, s1);
      }
      ln_stats2(a, b, 0.5f, oa, ra, ob, rb);
      CK(22);
      const uint32_t sh3 = sbase + O_B3 + (wp >> 1) * 4608 + (l >> 4) * 256 + (wp & 1) * 128 + ((((l >> 2) ^ (2 * cta + (wp & 1))) & 3) << 4) + (l & 3) * 4;
#pragma unroll
      for (int i = 0; i < 9; i++) {
        sts(sh3 + i * 512, pack_bf16(fmaf(a[2 * i], ra, oa), fmaf(a[2 * i + 1], ra, oa)));
        sts(sh3 + i * 512 + 64, pack_bf16(fmaf(b[2 * i], rb, ob), fmaf(b[2 * i + 1], rb, ob)));
      }
      fence_async_smem();
      if (wp == 0) CKX(0);
      if (wp < 2 * H3G) bar_arrive(8, 32 + 64 * H3G); else bar_arrive(9, 288 - 64 * H3G);
      CK(23);
    }
  } else __syncthreads();

  const bool g2 = cta < 130 && (cta >> 1) != 56;
  const int z2 = cta < 112 ? cta : cta - 2, r = z2 >> 6;
  const int s2 = 128 * ((z2 >> 2) & 15), d2 = 144 * (z2 & 3);
  constexpr int XST = (33 + 36 - JSK - 1) % NST;
  constexpr int ST0 = (32 - JSK - 1) % NST, ST1 = 31 % NST;

  if (wg == 2) {
    asm volatile("setmaxnreg.dec.sync.aligned.u32 40;");
    if (wp == 8) {
      int st = rows ? 4 : 0, ph = 1;
#pragma unroll 1
      for (int kb = st; kb < 32; kb++) {
        if (rows && (kb >> 1) == 2) mbar_wait(full0 + 8 * (B_S4 - 4 + kb), 0);
        mbar_wait(empty0 + 8 * st, ph);
        if (elect()) {
          load_a1(st, kb);
          if (kb >= PF2K && kb < PF2K + PF2 && g2)
            prefetch_l2(reinterpret_cast<const uint8_t*>(p.w2) + (size_t)(36 * r + kb2_order(kb - PF2K)) * 262144 + (z2 & 63) * 4096, 4096);
        }
        __syncwarp();
        ring_next<false>(st, ph);
      }
      if (g2) {
        st++;
#pragma unroll 1
        for (int i = 0; i < 36; i++) {
          if (i == HOLDA) mbar_wait(full0 + 8 * B_GO, 0);
          mbar_wait(empty0 + 8 * st, ph);
          if (elect()) {
            mbar_expect(full0 + 8 * st, 16384 + 18432);
            tma3d_ef(sbase + st * STAGE, &maps.w2, 64 * (36 * r + kb2_order(i)), s2 >> 6, full0 + 8 * st);
          }
          __syncwarp();
          ring_next<true>(st, ph);
        }
      }
    } else if (wp >= 10) {
      const int sw = wp - 10;
      if (rows) {
        const CUtensorMap* mp = upin(&maps.h3[sw]);
        const uint32_t src = upin(sbase + O_B3 + sw * (H3G * 4608)), c0 = upin(64 * (cta & 15)), c1 = upin(18 * (cta >> 4)), c2 = upin(H3G * sw);
        unsigned* flag = pin(&sc->cnt[C_H3 + (cta >> 4) + 8 * sw]);
        bar_sync(8 + sw, sw ? 288 - 64 * H3G : 32 + 64 * H3G);
        if (!sw) CKX(1);
        if (sw) { mbar_wait(full0 + 8 * H3W, 0); CKX(7); }
        if (elect()) {
          tma_st3d(mp, src, c0, c1, c2);
          if (!sw) CKX(2);
          mbar_arrive(full0 + 8 * B_S4);
          bulk_commit_wait();
          if (!sw) CKX(3);
          mbar_arrive(full0 + 8 * B_S5);
          asm volatile("fence.acq_rel.gpu;" ::: "memory");
          red_add(flag, 1);
          if (!sw) CKX(4);
          TS(sw ? 24 : 13);
        }
        __syncwarp();
      }
      if (sw && g2) {
        mbar_wait(full0 + 8 * 5, 0);
#pragma unroll 1
        for (int i = 0; i < 36; i++) { sc->part[z2 * 1152 + 32 * i + l] = make_uint4(tag1 ^ 1, 0, 0, 0); __nanosleep(100); }
        __syncwarp();
      }
      const uint32_t stg = sbase + (sw ? ST1 : ST0) * STAGE;
      const int kbA = (f1 >> 6) + (helper ? 2 : 1) * (sw ^ flip), kbB = helper ? (f1 >> 6) + 1 : kbA;
      const int dB = helper ? d1 + 32 * sw : d1 + 96;
      uint8_t* const uA = upin(sc->u + ((size_t)kbA * D_ + d1) * 128);
      uint8_t* const uB = upin(sc->u + ((size_t)kbB * D_ + dB) * 128);
      unsigned* const fA = pin(&sc->cnt[C_U + kbA]);
      unsigned* const fB = pin(&sc->cnt[C_U + kbB]);
      bar_sync(11 + sw, 160);
      if (elect()) { bulk_st(uA, stg, 96 * 128); TS(sw ? 31 : 30); }
      __syncwarp();
      bar_sync(13 + sw, 160);
      if (elect()) {
        bulk_st(uB, stg + 96 * 128, helper ? 32 * 128 : 64 * 128);
        if (helper) bulk_st(uB + (64 - 16 * sw) * 128, stg + 128 * 128, 16 * 128);
        bulk_commit_wait();
        mbar_arrive(empty0 + 8 * (sw ? ST1 : ST0));
        if (sw == 0) TS(26);
        asm volatile("fence.acq_rel.gpu;" ::: "memory");
        red_add(fA, 2);
        if (helper) red_add(fB, 1);
        TS(sw ? 23 : 17);
      }
      __syncwarp();
    } else {
      uint64_t ready = 0;
      int st = 0, ph = 1;
#pragma unroll 1
      for (int kb = 0; kb < 32; kb++) {
        const uint8_t* src = upin(sc->h3 + ((size_t)(kb * 18 + (d1 >> 5)) << 12));
        const uint32_t dst = upin(sbase + st * STAGE + a1bytes);
        if (rows && (kb >> 1) == 2) mbar_wait(full0 + 8 * (B_S4 - 4 + kb), 0);
        mbar_wait(empty0 + 8 * st, ph);
        wait_flags(sc->cnt + C_H3, 32, (kb & 7) + (kb < 8 * H3G ? 0 : 8), 16 * ep, ready);
        if (kb == 0) CKX(5);
        if (elect()) bulk_ld(dst, src, STAGE - a1bytes, full0 + 8 * st);
        if (kb == 0) CKX(6);
        if (kb == 5) CKX(8);
        if (kb == 8 * H3G) CKX(9);
        ring_next<false>(st, ph);
      }
      if (g2) {
        ready = 0;
        st++;
#pragma unroll 1
        for (int i = 0; i < 72; i++) {
          if (i == 36) ready = 0;
          const int kb = kb2_order(i < 36 ? i : i - 36), hf = r ^ (i >= 36);
          const uint8_t* src = upin(sc->u + ((size_t)(36 * r + kb) * D_ + d2) * 128);
          const uint32_t dst = upin(sbase + st * STAGE + 16384);
          if (i <= 36) mbar_wait(empty0 + 8 * st, ph);
          wait_flags(sc->cnt + C_U + 36 * hf, 36, kb, 8 * ep, ready);
          if (i < 36) {
            if (elect()) {
              bulk_ld(dst, src, 18432, full0 + 8 * st);
              if (i == GOAT) mbar_arrive(full0 + 8 * B_GO);
            }
            ring_next<true>(st, ph);
          } else if (ready == ~0ull) break;
        }
        if (l == 0) mbar_expect(full0 + 8 * XST, 18432);
        __syncwarp();
        if (l < 3) tma2d(sbase + XST * STAGE + 18432 + l * 6144, &maps.x1, d2 + 48 * l, s2 + 64 * (r ^ 1), full0 + 8 * XST);
        __syncwarp();
      }
    }
  } else {
    asm volatile("setmaxnreg.inc.sync.aligned.u32 232;");
    const int wgu = wg;
    constexpr uint32_t sb4 = sbase >> 4;
    const int w = wp & 3;
    Ring rg = {0, 0};
    uint32_t* const x1p = sc->x1 + (size_t)(cta + 256 * wp) * 288 + l;
    float acc[80];
    constexpr uint32_t LA = (8192 >> 4) << 16, LB = (4096 >> 4) << 16;
    {
      const int fa = f1 + (helper ? 128 : 64) * (wg ^ flip) + 16 * w + g, fb = helper ? f1 + 64 + 16 * w + g : fa;
      const float a0 = 0.5f * __bfloat162float(p.b1[fa]), a1 = 0.5f * __bfloat162float(p.b1[fa + 8]);
      const float b0 = 0.5f * __bfloat162float(p.b1[fb]), b1 = 0.5f * __bfloat162float(p.b1[fb + 8]);
#pragma unroll
      for (int i = 0; i < 80; i++) acc[i] = i < 48 ? ((i & 2) ? a1 : a0) : ((i & 2) ? b1 : b0);
      reg_fence(acc);
    }
    if (!helper) gemm_main<0>(acc, sb4 + (wgu ^ flip) * 512 + LA, 0, sb4 + 1024 + LB, 0, wgu, rg, x1p, xr);
    else {
      float ac2[80];
#pragma unroll
      for (int i = 0; i < 72; i++) asm volatile("mov.b32 %0, %1;" : "=f"(ac2[i]) : "f"(acc[i]));
      gemm_main<1>(ac2, sb4 + (wgu ^ flip) * 1024 + LA, sb4 + 512 + LA, sb4 + 1536 + LB, sb4 + 1536 + (wgu ? 256 + LB + (2 << 16) : 2 * LB), wgu, rg, x1p, xr);
#pragma unroll
      for (int i = 0; i < 72; i++) asm volatile("mov.b32 %0, %1;" : "=f"(acc[i]) : "f"(ac2[i]));
    }
    if (t128 == 0) TS(wg ? 16 : 6);
    {
      const int mi = l >> 3, rr = l & 7;
      const uint32_t ad = sbase + (wg ? ST1 : ST0) * STAGE + (8 * (mi >> 1) + rr) * 128 + (((2 * w + (mi & 1)) ^ rr) << 4);
      float z[2][16];
#pragma unroll
      for (int j = -1; j <= 5; j++) {
        if (j >= 1) {
          const float* a = &acc[16 * (j - 1)];
          const float* tt = z[(j - 1) & 1];
#pragma unroll
          for (int h = 0; h < 16; h += 8)
            stmatrix4t(ad + (2 * (j - 1) + (h >> 3)) * 2048, pack_bf16(fmaf(a[h], tt[h], a[h]), fmaf(a[h + 1], tt[h + 1], a[h + 1])),
                       pack_bf16(fmaf(a[h + 2], tt[h + 2], a[h + 2]), fmaf(a[h + 3], tt[h + 3], a[h + 3])),
                       pack_bf16(fmaf(a[h + 4], tt[h + 4], a[h + 4]), fmaf(a[h + 5], tt[h + 5], a[h + 5])),
                       pack_bf16(fmaf(a[h + 6], tt[h + 6], a[h + 6]), fmaf(a[h + 7], tt[h + 7], a[h + 7])));
        }
        if (j >= 0 && j < 5) {
#pragma unroll
          for (int e = 0; e < 16; e++) asm("tanh.approx.f32 %0, %0;" : "+f"(z[j & 1][e]));
        }
        if (j < 4) {
#pragma unroll
          for (int e = 0; e < 16; e++) z[(j + 1) & 1][e] = gelu_arg(acc[16 * (j + 1) + e]);
        }
        if (j == 3 || j == 5) { fence_async_smem(); asm volatile("bar.arrive %0, 160;" ::"r"((j == 3 ? 11 : 13) + wgu) : "memory"); }
        if (j < 5) {
          if (j >= 0) reg_fence(z[j & 1]);
          if (j < 4) reg_fence(z[(j + 1) & 1]);
          if (__builtin_expect(wp == 0x7ffffff0 + j, 0)) __trap();
          reg_fence(acc);
        }
      }
      if (t128 == 0) TS(wg ? 29 : 28);
    }
    if (g2) {
      const int mb = wgu ^ r;
      uint32_t gb[18];
      {
        float a0 = 0.f, a1 = 0.f;
        if (wgu) {
          a0 = __bfloat162float(p.b2[s2 + 64 * mb + 16 * w + g]); a1 = __bfloat162float(p.b2[s2 + 64 * mb + 16 * w + 8 + g]);
          int it = 0;
          uint32_t bad;
          do {
            bad = 0;
#pragma unroll
            for (int i = 0; i < 18; i++) {
              const uint2 v = ld_rlx2(sc->mod + 3 * D_ + d2 + 8 * i + 2 * t);
              bad |= (v.x ^ tag16) | (v.y ^ tag16);
              gb[i] = __byte_perm(v.x, v.y, 0x7632);
            }
          } while (any(bad & 0xffffu) && ++it < SPIN_MAX);
        }
#pragma unroll
        for (int i = 0; i < 72; i++) acc[i] = (i & 2) ? a1 : a0;
      }
      rg.st++;
      gemm_main<3>(acc, sb4 + mb * 512 + LA, 0, sb4 + 1024 + (1 << 16), 0, wgu, rg, x1p, xr);
      if (t128 == 0) TS(wg ? 20 : 19);
      const uint32_t sx = sbase + XST * STAGE;
      if (wgu == 0) {
        uint4* dst = sc->part + z2 * 1152 + t128;
#pragma unroll
        for (int j = 0; j < 9; j++) {
          const float* a = &acc[8 * j];
          dst[j * 128] = make_uint4(set_tag(pack_bf16(a[0], a[1]), tag1), pack_bf16(a[2], a[3]), pack_bf16(a[4], a[5]), pack_bf16(a[6], a[7]));
        }
        if (tid == 0) TS(21);
        const uint4* src = sc->part + (z2 ^ 64) * 1152 + t128;
        uint4 v[9];
        uint32_t bad;
        int it = 0;
        do {
#pragma unroll
          for (int j = 0; j < 9; j++) v[j] = ld_rlx4(src + j * 128);
          bad = v[8].x ^ tag1;
#pragma unroll
          for (int j = 0; j < 8; j += 2) bad |= diff2(v[j].x, v[j + 1].x, tag1);
        } while (any(bad & 1) && ++it < SPIN_MAX);
#pragma unroll
        for (int j = 0; j < 9; j++) sts4(sx + t128 * 16 + j * 2048, v[j].x, v[j].y, v[j].z, v[j].w);
        bar_arrive(2 + w, 64);
        if (w == 0) {
#pragma unroll 1
          for (int i = 0; i < 3; i++) {
            bar_sync(11 + i, 160);
            if (elect()) tma_st2d(&maps.out, sx + 18432 + i * 6144, d2 + 48 * i, s2 + 64 * (r ^ 1));
            __syncwarp();
          }
          if (elect()) { bulk_commit_wait_read(); TS(22); }
          __syncwarp();
        }
      } else {
        mbar_wait(full0 + 8 * XST, rg.ph);
        bar_sync(2 + w, 64);
        if (t128 == 0) TS(5);
        if (tid == 128 && cta == 0) sc->cnt[C_EP] = ep;
        const uint32_t xa = sx + 18432 + (16 * w + (l & 15)) * 96 + (l >> 4) * 16;
#pragma unroll
        for (int c = 0; c < 3; c++) {
          uint32_t pv[3][4], xv[3][4];
#pragma unroll
          for (int j = 0; j < 3; j++) {
            asm volatile("ld.shared.v4.b32 {%0,%1,%2,%3}, [%4];" : "=r"(pv[j][0]), "=r"(pv[j][1]), "=r"(pv[j][2]), "=r"(pv[j][3]) : "r"(sx + t128 * 16 + (3 * c + j) * 2048) : "memory");
            asm volatile("ldmatrix.sync.aligned.m8n8.x4.shared.b16 {%0,%1,%2,%3}, [%4];" : "=r"(xv[j][0]), "=r"(xv[j][1]), "=r"(xv[j][2]), "=r"(xv[j][3]) : "r"(xa + c * 6144 + j * 32) : "memory");
          }
#pragma unroll
          for (int j = 0; j < 3; j++) {
            const float* a = &acc[8 * (3 * c + j)];
            uint32_t o[4];
#pragma unroll
            for (int e = 0; e < 4; e++)
              o[e] = hadd2(xv[j][e], hmul2(gb[2 * (3 * c + j) + (e >> 1)], pack_bf16(a[2 * e] + bf_lo(pv[j][e]), a[2 * e + 1] + bf_hi(pv[j][e]))));
            stmatrix4(xa + c * 6144 + j * 32, o[0], o[1], o[2], o[3]);
          }
          fence_async_smem();
          asm volatile("bar.arrive %0, 160;" ::"r"(11 + c) : "memory");
        }
        if (t128 == 0) TS(7);
        __syncwarp();
      }
    }
  }
}

typedef CUresult (*EncodeFn)(CUtensorMap*, CUtensorMapDataType, cuuint32_t, void*, const cuuint64_t*, const cuuint64_t*, const cuuint32_t*,
                             const cuuint32_t*, CUtensorMapInterleave, CUtensorMapSwizzle, CUtensorMapL2promotion, CUtensorMapFloatOOBfill);

struct Dim { cuuint64_t n, stride; cuuint32_t box; };
template <int RANK>
void make_map(EncodeFn enc, CUtensorMap* m, bool words, int swz, const void* ptr, const Dim (&d)[RANK]) {
  cuuint64_t gd[RANK], gs[RANK];
  cuuint32_t bx[RANK], es[RANK];
  for (int i = 0; i < RANK; i++) { gd[i] = d[i].n; gs[i] = d[i].stride; bx[i] = d[i].box; es[i] = 1; }
  enc(m, words ? CU_TENSOR_MAP_DATA_TYPE_UINT32 : CU_TENSOR_MAP_DATA_TYPE_BFLOAT16, RANK, const_cast<void*>(ptr), gd, gs + 1, bx, es,
      CU_TENSOR_MAP_INTERLEAVE_NONE, static_cast<CUtensorMapSwizzle>(swz),
      swz == 3 ? CU_TENSOR_MAP_L2_PROMOTION_L2_256B : CU_TENSOR_MAP_L2_PROMOTION_NONE, CU_TENSOR_MAP_FLOAT_OOB_FILL_NONE);
}

}

extern "C" void kernel_launch(void* const* d_in, const int* in_sizes, int n_in, void* d_out, int out_size) {
  (void)in_sizes; (void)n_in; (void)out_size;
  static EncodeFn enc = nullptr;
  static void *sptr = nullptr, *tptr = nullptr;
  if (!enc) {
    void* f = nullptr; cudaDriverEntryPointQueryResult qr;
    cudaGetDriverEntryPoint("cuTensorMapEncodeTiled", &f, cudaEnableDefault, &qr);
    enc = reinterpret_cast<EncodeFn>(f);
    cudaFuncSetAttribute(fused_kernel, cudaFuncAttributeMaxDynamicSharedMemorySize, SMEM_BYTES);
    cudaGetSymbolAddress(&sptr, g_s);
    cudaGetSymbolAddress(&tptr, T_TAB);
  }
  Params p;
  p.x = (const __nv_bfloat16*)d_in[0]; p.wr = (const __nv_bfloat16*)d_in[1]; p.wi = (const __nv_bfloat16*)d_in[2];
  p.b1 = (const __nv_bfloat16*)d_in[5]; p.b2 = (const __nv_bfloat16*)d_in[7];
  p.c = (const __nv_bfloat16*)d_in[8]; p.wmod = (const __nv_bfloat16*)d_in[9];
  p.w1 = (const __nv_bfloat16*)d_in[4]; p.w2 = (const __nv_bfloat16*)d_in[6];
  p.s = static_cast<Scratch*>(sptr); p.tab = static_cast<const uint4*>(tptr);
  Maps maps;
  make_map<4>(enc, &maps.w1a, false, 3, p.w1, {{64, 0, 64}, {16, 128 * 2 * F_, 4}, {128, 2 * F_, 16}, {72, 128, 2}});
  make_map<4>(enc, &maps.w1b, false, 3, p.w1, {{64, 0, 64}, {16, 128 * 2 * F_, 4}, {128, 2 * F_, 16}, {72, 128, 3}});
  make_map<3>(enc, &maps.w2, false, 3, p.w2, {{64, 0, 64}, {F_, 2 * S_, 64}, {32, 128, 2}});
  make_map<2>(enc, &maps.x1, false, 0, p.s->x1, {{D_, 0, 48}, {S_, 2 * D_, 64}});
  make_map<2>(enc, &maps.out, false, 0, d_out, {{D_, 0, 48}, {S_, 2 * D_, 64}});
  make_map<2>(enc, &maps.z1, true, 0, p.s->z1, {{5120, 0, 40}, {120, 20480, 60}});
  for (int i = 0; i < 2; i++) make_map<2>(enc, &maps.z2[i], true, 0, p.s->z2, {{4800, 0, i ? 16u : 24u}, {128, 19200, 128}});
  for (int i = 0; i < 4; i++) make_map<2>(enc, &maps.wf[i], false, 2 - (i & 1), (i & 2) ? p.wi : p.wr, {{16 * DF_, 0, (i & 1) ? 16u : 32u}, {128, 32 * DF_, 128}});
  make_map<2>(enc, &maps.wm, false, 1, p.wmod, {{6 * D_, 0, 16}, {D_, 12 * D_, 192}});
  for (int i = 0; i < 2; i++) make_map<3>(enc, &maps.h3[i], true, 0, p.s->h3, {{1024, 0, 64}, {144, 4096, 18}, {4, 144 * 4096, i ? 4u - H3G : H3G}});
  fused_kernel<<<NCTA, NTHR, SMEM_BYTES, cudaStreamPerThread>>>(p, maps);
}
```

```cpp
#include <cuda_runtime.h>
#include <cuda_bf16.h>
#include <cuda.h>
#include <stdint.h>

namespace {

constexpr int S_ = 2048, D_ = 576, DF_ = 289, F_ = 4608;
constexpr int NCTA = 132, NTHR = 384;
constexpr int STAGE = 36864, NST = 6;
constexpr uint32_t sbase = 1024, full0 = sbase + NST * STAGE, empty0 = full0 + 8 * NST, red = full0 + 256;
constexpr int SMEM_BYTES = NST * STAGE + 256 + 512 + 4 * D_ + 512;
constexpr int O_NRM = 0, O_B1 = 19456, O_Z1 = 38912, O_P2 = 59392, O_ST = 3 * STAGE;
constexpr int O_RAW = 4 * STAGE;
constexpr int O_IN = 4 * STAGE, O_Y = O_IN + 19456, O_B3 = O_IN + 38912, O_MOD = O_IN + 57344;

__device__ __align__(128) const uint32_t T_TAB[5632] = {
0x3f803f80,0xbf803f80,0x3f803f80,0xbf803f80,0x3f803f80,0xbf803f80,0x3f803f80,0xbf803f80,0x3f803f80,0xbf803f80,0x3f803f80,0xbf803f80,
0x3f803f80,0xbf803f80,0x3f803f80,0xbf803f80,0x3f7f3f80,0xbdc90000,0x3f223f35,0xbf46bf35,0x3f753f7b,0xbe95be48,0x3ef13f0e,0xbf62bf55,
0x3f623f6d,0xbef1bec4,0x3e953ec4,0xbf75bf6d,0x3f463f55,0xbf22bf0e,0x3dc93e48,0xbf7fbf7b,0x3f7b3f80,0xbe480000,0xbe480000,0xbf7bbf80,
0x3f553f6d,0xbf0ebec4,0xbf0ebec4,0xbf55bf6d,0x3f0e3f35,0xbf55bf35,0xbf55bf35,0xbf0ebf35,0x3e483ec4,0xbf7bbf6d,0xbf7bbf6d,0xbe48bec4,
0x3f753f80,0xbe950000,0xbf62bf35,0xbef1bf35,0x3f223f55,0xbf46bf0e,0xbf7fbf7b,0x3dc9be48,0x3dc93ec4,0xbf7fbf6d,0xbf46bf6d,0x3f223ec4,
0xbef1be48,0xbf62bf7b,0xbe95bf0e,0x3f753f55,0x3f6d3f80,0xbec40000,0xbf6dbf80,0x3ec40000,0x3ec43f35,0xbf6dbf35,0xbec4bf35,0x3f6d3f35,
0xbec40000,0xbf6dbf80,0x3ec40000,0x3f6d3f80,0xbf6dbf35,0xbec4bf35,0x3f6d3f35,0x3ec43f35,0x3f623f80,0xbef10000,0xbe95bf35,0x3f753f35,
0x3dc93f0e,0xbf7fbf55,0x3f223e48,0x3f463f7b,0xbf46bec4,0xbf22bf6d,0x3f7f3f6d,0xbdc93ec4,0xbf75bf7b,0x3e95be48,0x3ef13f55,0xbf62bf0e,
0x3f553f80,0xbf0e0000,0x3f0e0000,0x3f553f80,0xbe483ec4,0xbf7bbf6d,0x3f7b3f6d,0xbe483ec4,0xbf7bbf35,0xbe48bf35,0x3e483f35,0xbf7bbf35,
0xbf0ebf6d,0x3f553ec4,0xbf55bec4,0xbf0ebf6d,0x3f463f80,0xbf220000,0x3f7f3f35,0x3dc93f35,0xbef13e48,0xbf62bf7b,0x3e953f55,0xbf75bf0e,
0xbf75bf6d,0x3e95bec4,0xbf62bec4,0xbef1bf6d,0x3dc9bf0e,0x3f7f3f55,0xbf22bf7b,0x3f463e48,0x3f353f80,0xbf350000,0x3f353f80,0xbf350000,
0xbf350000,0xbf35bf80,0xbf350000,0xbf35bf80,0xbf35bf80,0x3f350000,0xbf35bf80,0x3f350000,0x3f350000,0x3f353f80,0x3f350000,0x3f353f80,
0x3f223f80,0xbf460000,0xbdc93f35,0xbf7fbf35,0xbf62be48,0xbef1bf7b,0xbf75bf55,0x3e95bf0e,0xbe95bf6d,0x3f753ec4,0x3ef1bec4,0x3f623f6d,
0x3f7f3f0e,0x3dc93f55,0x3f463f7b,0xbf223e48,0x3f0e3f80,0xbf550000,0xbf550000,0xbf0ebf80,0xbf7bbec4,0xbe48bf6d,0xbe48bf6d,0x3f7b3ec4,
0x3e48bf35,0x3f7b3f35,0x3f7b3f35,0xbe483f35,0x3f553f6d,0xbf0e3ec4,0xbf0e3ec4,0xbf55bf6d,0x3ef13f80,0xbf620000,0xbf75bf35,0x3e95bf35,
0xbf7fbf0e,0x3dc9bf55,0x3f46be48,0x3f223f7b,0x3f22bec4,0x3f463f6d,0x3dc93f6d,0xbf7fbec4,0x3e953f7b,0xbf75be48,0xbf62bf55,0x3ef1bf0e,
0x3ec43f80,0xbf6d0000,0xbec4bf80,0x3f6d0000,0xbf6dbf35,0x3ec4bf35,0x3f6d3f35,0xbec43f35,0x3f6d0000,0x3ec43f80,0xbf6d0000,0xbec4bf80,
0xbec43f35,0xbf6dbf35,0x3ec4bf35,0x3f6d3f35,0x3e953f80,0xbf750000,0x3ef1bf35,0x3f623f35,0xbf46bf55,0x3f22bf0e,0x3dc93f7b,0xbf7fbe48,
0x3f7f3ec4,0xbdc93f6d,0xbf22bf6d,0x3f46bec4,0xbf623e48,0xbef1bf7b,0x3f753f0e,0xbe953f55,0x3e483f80,0xbf7b0000,0x3f7b0000,0x3e483f80,
0xbf0ebf6d,0x3f55bec4,0xbf553ec4,0xbf0ebf6d,0x3f553f35,0xbf0e3f35,0x3f0ebf35,0x3f553f35,0xbf7bbec4,0x3e48bf6d,0xbe483f6d,0xbf7bbec4,
0x3dc93f80,0xbf7f0000,0x3f463f35,0xbf223f35,0xbe95bf7b,0x3f75be48,0xbf62bf0e,0x3ef1bf55,0x3ef13f6d,0xbf623ec4,0x3f753ec4,0xbe953f6d,
0xbf22bf55,0x3f46bf0e,0xbf7fbe48,0x3dc9bf7b,0x3f80,0xbf800000,0x3f80,0xbf800000,0xbf80,0x3f800000,0xbf80,0x3f800000,
0x3f80,0xbf800000,0x3f80,0xbf800000,0xbf80,0x3f800000,0xbf80,0x3f800000,0xbdc93f80,0xbf7f0000,0xbf463f35,0xbf22bf35,
0x3e95bf7b,0x3f753e48,0x3f62bf0e,0x3ef13f55,0xbef13f6d,0xbf62bec4,0xbf753ec4,0xbe95bf6d,0x3f22bf55,0x3f463f0e,0x3f7fbe48,0x3dc93f7b,
0xbe483f80,0xbf7b0000,0xbf7b0000,0x3e48bf80,0x3f0ebf6d,0x3f553ec4,0x3f553ec4,0xbf0e3f6d,0xbf553f35,0xbf0ebf35,0xbf0ebf35,0x3f55bf35,
0x3f7bbec4,0x3e483f6d,0x3e483f6d,0xbf7b3ec4,0xbe953f80,0xbf750000,0xbef1bf35,0x3f62bf35,0x3f46bf55,0x3f223f0e,0xbdc93f7b,0xbf7f3e48,
0xbf7f3ec4,0xbdc9bf6d,0x3f22bf6d,0x3f463ec4,0x3f623e48,0xbef13f7b,0xbf753f0e,0xbe95bf55,0xbec43f80,0xbf6d0000,0x3ec4bf80,0x3f6d0000,
0x3f6dbf35,0x3ec43f35,0xbf6d3f35,0xbec4bf35,0xbf6d0000,0x3ec4bf80,0x3f6d0000,0xbec43f80,0x3ec43f35,0xbf6d3f35,0xbec4bf35,0x3f6dbf35,
0xbef13f80,0xbf620000,0x3f75bf35,0x3e953f35,0x3f7fbf0e,0x3dc93f55,0xbf46be48,0x3f22bf7b,0xbf22bec4,0x3f46bf6d,0xbdc93f6d,0xbf7f3ec4,
0xbe953f7b,0xbf753e48,0x3f62bf55,0x3ef13f0e,0xbf0e3f80,0xbf550000,0x3f550000,0xbf0e3f80,0x3f7bbec4,0xbe483f6d,0x3e48bf6d,0x3f7bbec4,
0xbe48bf35,0x3f7bbf35,0xbf7b3f35,0xbe48bf35,0xbf553f6d,0xbf0ebec4,0x3f0e3ec4,0xbf553f6d,0xbf223f80,0xbf460000,0x3dc93f35,0xbf7f3f35,
0x3f62be48,0xbef13f7b,0x3f75bf55,0x3e953f0e,0x3e95bf6d,0x3f75bec4,0xbef1bec4,0x3f62bf6d,0xbf7f3f0e,0x3dc9bf55,0xbf463f7b,0xbf22be48,
0xbf353f80,0xbf350000,0xbf353f80,0xbf350000,0x3f350000,0xbf353f80,0x3f350000,0xbf353f80,0x3f35bf80,0x3f350000,0x3f35bf80,0x3f350000,
0xbf350000,0x3f35bf80,0xbf350000,0x3f35bf80,0xbf463f80,0xbf220000,0xbf7f3f35,0x3dc9bf35,0x3ef13e48,0xbf623f7b,0xbe953f55,0xbf753f0e,
0x3f75bf6d,0x3e953ec4,0x3f62bec4,0xbef13f6d,0xbdc9bf0e,0x3f7fbf55,0x3f22bf7b,0x3f46be48,0xbf553f80,0xbf0e0000,0xbf0e0000,0x3f55bf80,
0x3e483ec4,0xbf7b3f6d,0xbf7b3f6d,0xbe48bec4,0x3f7bbf35,0xbe483f35,0xbe483f35,0xbf7b3f35,0x3f0ebf6d,0x3f55bec4,0x3f55bec4,0xbf0e3f6d,
0xbf623f80,0xbef10000,0x3e95bf35,0x3f75bf35,0xbdc93f0e,0xbf7f3f55,0xbf223e48,0x3f46bf7b,0x3f46bec4,0xbf223f6d,0xbf7f3f6d,0xbdc9bec4,
0x3f75bf7b,0x3e953e48,0xbef13f55,0xbf623f0e,0xbf6d3f80,0xbec40000,0x3f6dbf80,0x3ec40000,0xbec43f35,0xbf6d3f35,0x3ec4bf35,0x3f6dbf35,
0x3ec40000,0xbf6d3f80,0xbec40000,0x3f6dbf80,0x3f6dbf35,0xbec43f35,0xbf6d3f35,0x3ec4bf35,0xbf753f80,0xbe950000,0x3f62bf35,0xbef13f35,
0xbf223f55,0xbf463f0e,0x3f7fbf7b,0x3dc93e48,0xbdc93ec4,0xbf7f3f6d,0x3f46bf6d,0x3f22bec4,0x3ef1be48,0xbf623f7b,0x3e95bf0e,0x3f75bf55,
0xbf7b3f80,0xbe480000,0x3e480000,0xbf7b3f80,0xbf553f6d,0xbf0e3ec4,0x3f0ebec4,0xbf553f6d,0xbf0e3f35,0xbf553f35,0x3f55bf35,0xbf0e3f35,
0xbe483ec4,0xbf7b3f6d,0x3f7bbf6d,0xbe483ec4,0xbf7f3f80,0xbdc90000,0xbf223f35,0xbf463f35,0xbf753f7b,0xbe953e48,0xbef13f0e,0xbf623f55,
0xbf623f6d,0xbef13ec4,0xbe953ec4,0xbf753f6d,0xbf463f55,0xbf223f0e,0xbdc93e48,0xbf7f3f7b,0x3f803f80,0xbf803f80,0x3f803f80,0xbf803f80,
0x3f803f80,0xbf803f80,0x3f803f80,0xbf803f80,0x3f803f80,0xbf803f80,0x3f803f80,0xbf803f80,0x3f803f80,0xbf803f80,0x3f803f80,0xbf803f80,
0xbdc90000,0xbf7fbf80,0xbf46bf35,0xbf22bf35,0xbe95be48,0xbf75bf7b,0xbf62bf55,0xbef1bf0e,0xbef1bec4,0xbf62bf6d,0xbf75bf6d,0xbe95bec4,
0xbf22bf0e,0xbf46bf55,0xbf7fbf7b,0xbdc9be48,0xbf7bbf80,0x3e480000,0x3e480000,0x3f7b3f80,0xbf55bf6d,0x3f0e3ec4,0x3f0e3ec4,0x3f553f6d,
0xbf0ebf35,0x3f553f35,0x3f553f35,0x3f0e3f35,0xbe48bec4,0x3f7b3f6d,0x3f7b3f6d,0x3e483ec4,0x3e950000,0x3f753f80,0x3ef13f35,0xbf62bf35,
0x3f463f0e,0x3f223f55,0xbdc93e48,0xbf7fbf7b,0x3f7f3f6d,0x3dc93ec4,0xbf22bec4,0xbf46bf6d,0x3f623f7b,0xbef1be48,0xbf75bf55,0xbe95bf0e,
0x3f6d3f80,0xbec40000,0xbf6dbf80,0x3ec40000,0x3ec43f35,0xbf6dbf35,0xbec4bf35,0x3f6d3f35,0xbec40000,0xbf6dbf80,0x3ec40000,0x3f6d3f80,
0xbf6dbf35,0xbec4bf35,0x3f6d3f35,0x3ec43f35,0xbef10000,0xbf62bf80,0x3f753f35,0x3e953f35,0xbf7fbf55,0xbdc9bf0e,0x3f463f7b,0xbf22be48,
0xbf22bf6d,0x3f463ec4,0xbdc93ec4,0xbf7fbf6d,0x3e95be48,0x3f753f7b,0xbf62bf0e,0xbef1bf55,0xbf55bf80,0x3f0e0000,0xbf0e0000,0xbf55bf80,
0x3e48bec4,0x3f7b3f6d,0xbf7bbf6d,0x3e48bec4,0x3f7b3f35,0x3e483f35,0xbe48bf35,0x3f7b3f35,0x3f0e3f6d,0xbf55bec4,0x3f553ec4,0x3f0e3f6d,
0x3f220000,0x3f463f80,0xbdc9bf35,0x3f7f3f35,0x3f623f7b,0xbef13e48,0x3f753f0e,0x3e953f55,0xbe953ec4,0xbf75bf6d,0x3ef13f6d,0xbf62bec4,
0xbf7fbf55,0x3dc9bf0e,0xbf46be48,0xbf22bf7b,0x3f353f80,0xbf350000,0x3f353f80,0xbf350000,0xbf350000,0xbf35bf80,0xbf350000,0xbf35bf80,
0xbf35bf80,0x3f350000,0xbf35bf80,0x3f350000,0x3f350000,0x3f353f80,0x3f350000,0x3f353f80,0xbf460000,0xbf22bf80,0xbf7fbf35,0x3dc9bf35,
0xbef1bf7b,0x3f623e48,0x3e95bf0e,0x3f753f55,0x3f753ec4,0x3e953f6d,0x3f623f6d,0xbef13ec4,0x3dc93f55,0xbf7fbf0e,0xbf223e48,0xbf46bf7b,
0xbf0ebf80,0x3f550000,0x3f550000,0x3f0e3f80,0x3f7b3ec4,0x3e483f6d,0x3e483f6d,0xbf7bbec4,0xbe483f35,0xbf7bbf35,0xbf7bbf35,0x3e48bf35,
0xbf55bf6d,0x3f0ebec4,0x3f0ebec4,0x3f553f6d,0x3f620000,0x3ef13f80,0xbe953f35,0xbf75bf35,0xbdc93f55,0xbf7fbf0e,0xbf22bf7b,0x3f46be48,
0xbf46bf6d,0x3f22bec4,0x3f7f3ec4,0x3dc93f6d,0x3f753e48,0x3e953f7b,0xbef13f0e,0xbf62bf55,0x3ec43f80,0xbf6d0000,0xbec4bf80,0x3f6d0000,
0xbf6dbf35,0x3ec4bf35,0x3f6d3f35,0xbec43f35,0x3f6d0000,0x3ec43f80,0xbf6d0000,0xbec4bf80,0xbec43f35,0xbf6dbf35,0x3ec4bf35,0x3f6d3f35,
0xbf750000,0xbe95bf80,0x3f623f35,0xbef13f35,0x3f22bf0e,0x3f463f55,0xbf7fbe48,0xbdc9bf7b,0xbdc93f6d,0xbf7fbec4,0x3f46bec4,0x3f223f6d,
0xbef1bf7b,0x3f62be48,0xbe953f55,0xbf75bf0e,0xbe48bf80,0x3f7b0000,0xbf7b0000,0xbe48bf80,0x3f0e3f6d,0xbf553ec4,0x3f55bec4,0x3f0e3f6d,
0xbf55bf35,0x3f0ebf35,0xbf0e3f35,0xbf55bf35,0x3f7b3ec4,0xbe483f6d,0x3e48bf6d,0x3f7b3ec4,0x3f7f0000,0x3dc93f80,0x3f22bf35,0x3f463f35,
0xbf753e48,0xbe95bf7b,0xbef13f55,0xbf62bf0e,0x3f62bec4,0x3ef13f6d,0x3e95bf6d,0x3f753ec4,0xbf463f0e,0xbf22bf55,0xbdc93f7b,0xbf7fbe48,
0x3f80,0xbf800000,0x3f80,0xbf800000,0xbf80,0x3f800000,0xbf80,0x3f800000,0x3f80,0xbf800000,0x3f80,0xbf800000,
0xbf80,0x3f800000,0xbf80,0x3f800000,0xbf7f0000,0x3dc9bf80,0xbf22bf35,0x3f46bf35,0x3f753e48,0xbe953f7b,0x3ef13f55,0xbf623f0e,
0xbf62bec4,0x3ef1bf6d,0xbe95bf6d,0x3f75bec4,0x3f463f0e,0xbf223f55,0x3dc93f7b,0xbf7f3e48,0x3e48bf80,0x3f7b0000,0x3f7b0000,0xbe483f80,
0xbf0e3f6d,0xbf55bec4,0xbf55bec4,0x3f0ebf6d,0x3f55bf35,0x3f0e3f35,0x3f0e3f35,0xbf553f35,0xbf7b3ec4,0xbe48bf6d,0xbe48bf6d,0x3f7bbec4,
0x3f750000,0xbe953f80,0xbf623f35,0xbef1bf35,0xbf22bf0e,0x3f46bf55,0x3f7fbe48,0xbdc93f7b,0x3dc93f6d,0xbf7f3ec4,0xbf46bec4,0x3f22bf6d,
0x3ef1bf7b,0x3f623e48,0x3e953f55,0xbf753f0e,0xbec43f80,0xbf6d0000,0x3ec4bf80,0x3f6d0000,0x3f6dbf35,0x3ec43f35,0xbf6d3f35,0xbec4bf35,
0xbf6d0000,0x3ec4bf80,0x3f6d0000,0xbec43f80,0x3ec43f35,0xbf6d3f35,0xbec4bf35,0x3f6dbf35,0xbf620000,0x3ef1bf80,0x3e953f35,0xbf753f35,
0x3dc93f55,0xbf7f3f0e,0x3f22bf7b,0x3f463e48,0x3f46bf6d,0x3f223ec4,0xbf7f3ec4,0x3dc9bf6d,0xbf753e48,0x3e95bf7b,0x3ef13f0e,0xbf623f55,
0x3f0ebf80,0x3f550000,0xbf550000,0x3f0ebf80,0xbf7b3ec4,0x3e48bf6d,0xbe483f6d,0xbf7b3ec4,0x3e483f35,0xbf7b3f35,0x3f7bbf35,0x3e483f35,
0x3f55bf6d,0x3f0e3ec4,0xbf0ebec4,0x3f55bf6d,0x3f460000,0xbf223f80,0x3f7fbf35,0x3dc93f35,0x3ef1bf7b,0x3f62be48,0xbe95bf0e,0x3f75bf55,
0xbf753ec4,0x3e95bf6d,0xbf623f6d,0xbef1bec4,0xbdc93f55,0xbf7f3f0e,0x3f223e48,0xbf463f7b,0xbf353f80,0xbf350000,0xbf353f80,0xbf350000,
0x3f350000,0xbf353f80,0x3f350000,0xbf353f80,0x3f35bf80,0x3f350000,0x3f35bf80,0x3f350000,0xbf350000,0x3f35bf80,0xbf350000,0x3f35bf80,
0xbf220000,0x3f46bf80,0x3dc9bf35,0x3f7fbf35,0xbf623f7b,0xbef1be48,0xbf753f0e,0x3e95bf55,0x3e953ec4,0xbf753f6d,0xbef13f6d,0xbf623ec4,
0x3f7fbf55,0x3dc93f0e,0x3f46be48,0xbf223f7b,0x3f55bf80,0x3f0e0000,0x3f0e0000,0xbf553f80,0xbe48bec4,0x3f7bbf6d,0x3f7bbf6d,0x3e483ec4,
0xbf7b3f35,0x3e48bf35,0x3e48bf35,0x3f7bbf35,0xbf0e3f6d,0xbf553ec4,0xbf553ec4,0x3f0ebf6d,0x3ef10000,0xbf623f80,0xbf753f35,0x3e95bf35,
0x3f7fbf55,0xbdc93f0e,0xbf463f7b,0xbf223e48,0x3f22bf6d,0x3f46bec4,0x3dc93ec4,0xbf7f3f6d,0xbe95be48,0x3f75bf7b,0x3f62bf0e,0xbef13f55,
0xbf6d3f80,0xbec40000,0x3f6dbf80,0x3ec40000,0xbec43f35,0xbf6d3f35,0x3ec4bf35,0x3f6dbf35,0x3ec40000,0xbf6d3f80,0xbec40000,0x3f6dbf80,
0x3f6dbf35,0xbec43f35,0xbf6d3f35,0x3ec4bf35,0xbe950000,0x3f75bf80,0xbef13f35,0xbf623f35,0xbf463f0e,0x3f22bf55,0x3dc93e48,0xbf7f3f7b,
0xbf7f3f6d,0x3dc9bec4,0x3f22bec4,0xbf463f6d,0xbf623f7b,0xbef13e48,0x3f75bf55,0xbe953f0e,0x3f7bbf80,0x3e480000,0xbe480000,0x3f7bbf80,
0x3f55bf6d,0x3f0ebec4,0xbf0e3ec4,0x3f55bf6d,0x3f0ebf35,0x3f55bf35,0xbf553f35,0x3f0ebf35,0x3e48bec4,0x3f7bbf6d,0xbf7b3f6d,0x3e48bec4,
0x3dc90000,0xbf7f3f80,0x3f46bf35,0xbf223f35,0x3e95be48,0xbf753f7b,0x3f62bf55,0xbef13f0e,0x3ef1bec4,0xbf623f6d,0x3f75bf6d,0xbe953ec4,
0x3f22bf0e,0xbf463f55,0x3f7fbf7b,0xbdc93e48,0x3f803f80,0xbf803f80,0x3f803f80,0xbf803f80,0x3f803f80,0xbf803f80,0x3f803f80,0xbf803f80,
0x3f803f80,0xbf803f80,0x3f803f80,0xbf803f80,0x3f803f80,0xbf803f80,0x3f803f80,0xbf803f80,0xbf7fbf80,0x3dc90000,0xbf22bf35,0x3f463f35,
0xbf75bf7b,0x3e953e48,0xbef1bf0e,0x3f623f55,0xbf62bf6d,0x3ef13ec4,0xbe95bec4,0x3f753f6d,0xbf46bf55,0x3f223f0e,0xbdc9be48,0x3f7f3f7b,
0x3f7b3f80,0xbe480000,0xbe480000,0xbf7bbf80,0x3f553f6d,0xbf0ebec4,0xbf0ebec4,0xbf55bf6d,0x3f0e3f35,0xbf55bf35,0xbf55bf35,0xbf0ebf35,
0x3e483ec4,0xbf7bbf6d,0xbf7bbf6d,0xbe48bec4,0xbf75bf80,0x3e950000,0x3f623f35,0x3ef13f35,0xbf22bf55,0x3f463f0e,0x3f7f3f7b,0xbdc93e48,
0xbdc9bec4,0x3f7f3f6d,0x3f463f6d,0xbf22bec4,0x3ef13e48,0x3f623f7b,0x3e953f0e,0xbf75bf55,0x3f6d3f80,0xbec40000,0xbf6dbf80,0x3ec40000,
0x3ec43f35,0xbf6dbf35,0xbec4bf35,0x3f6d3f35,0xbec40000,0xbf6dbf80,0x3ec40000,0x3f6d3f80,0xbf6dbf35,0xbec4bf35,0x3f6d3f35,0x3ec43f35,
0xbf62bf80,0x3ef10000,0x3e953f35,0xbf75bf35,0xbdc9bf0e,0x3f7f3f55,0xbf22be48,0xbf46bf7b,0x3f463ec4,0x3f223f6d,0xbf7fbf6d,0x3dc9bec4,
0x3f753f7b,0xbe953e48,0xbef1bf55,0x3f623f0e,0x3f553f80,0xbf0e0000,0x3f0e0000,0x3f553f80,0xbe483ec4,0xbf7bbf6d,0x3f7b3f6d,0xbe483ec4,
0xbf7bbf35,0xbe48bf35,0x3e483f35,0xbf7bbf35,0xbf0ebf6d,0x3f553ec4,0xbf55bec4,0xbf0ebf6d,0xbf46bf80,0x3f220000,0xbf7fbf35,0xbdc9bf35,
0x3ef1be48,0x3f623f7b,0xbe95bf55,0x3f753f0e,0x3f753f6d,0xbe953ec4,0x3f623ec4,0x3ef13f6d,0xbdc93f0e,0xbf7fbf55,0x3f223f7b,0xbf46be48,
0x3f353f80,0xbf350000,0x3f353f80,0xbf350000,0xbf350000,0xbf35bf80,0xbf350000,0xbf35bf80,0xbf35bf80,0x3f350000,0xbf35bf80,0x3f350000,
0x3f350000,0x3f353f80,0x3f350000,0x3f353f80,0xbf22bf80,0x3f460000,0x3dc9bf35,0x3f7f3f35,0x3f623e48,0x3ef13f7b,0x3f753f55,0xbe953f0e,
0x3e953f6d,0xbf75bec4,0xbef13ec4,0xbf62bf6d,0xbf7fbf0e,0xbdc9bf55,0xbf46bf7b,0x3f22be48,0x3f0e3f80,0xbf550000,0xbf550000,0xbf0ebf80,
0xbf7bbec4,0xbe48bf6d,0xbe48bf6d,0x3f7b3ec4,0x3e48bf35,0x3f7b3f35,0x3f7b3f35,0xbe483f35,0x3f553f6d,0xbf0e3ec4,0xbf0e3ec4,0xbf55bf6d,
0xbef1bf80,0x3f620000,0x3f753f35,0xbe953f35,0x3f7f3f0e,0xbdc93f55,0xbf463e48,0xbf22bf7b,0xbf223ec4,0xbf46bf6d,0xbdc9bf6d,0x3f7f3ec4,
0xbe95bf7b,0x3f753e48,0x3f623f55,0xbef13f0e,0x3ec43f80,0xbf6d0000,0xbec4bf80,0x3f6d0000,0xbf6dbf35,0x3ec4bf35,0x3f6d3f35,0xbec43f35,
0x3f6d0000,0x3ec43f80,0xbf6d0000,0xbec4bf80,0xbec43f35,0xbf6dbf35,0x3ec4bf35,0x3f6d3f35,0xbe95bf80,0x3f750000,0xbef13f35,0xbf62bf35,
0x3f463f55,0xbf223f0e,0xbdc9bf7b,0x3f7f3e48,0xbf7fbec4,0x3dc9bf6d,0x3f223f6d,0xbf463ec4,0x3f62be48,0x3ef13f7b,0xbf75bf0e,0x3e95bf55,
0x3e483f80,0xbf7b0000,0x3f7b0000,0x3e483f80,0xbf0ebf6d,0x3f55bec4,0xbf553ec4,0xbf0ebf6d,0x3f553f35,0xbf0e3f35,0x3f0ebf35,0x3f553f35,
0xbf7bbec4,0x3e48bf6d,0xbe483f6d,0xbf7bbec4,0xbdc9bf80,0x3f7f0000,0xbf46bf35,0x3f22bf35,0x3e953f7b,0xbf753e48,0x3f623f0e,0xbef13f55,
0xbef1bf6d,0x3f62bec4,0xbf75bec4,0x3e95bf6d,0x3f223f55,0xbf463f0e,0x3f7f3e48,0xbdc93f7b,0x3f80,0xbf800000,0x3f80,0xbf800000,
0xbf80,0x3f800000,0xbf80,0x3f800000,0x3f80,0xbf800000,0x3f80,0xbf800000,0xbf80,0x3f800000,0xbf80,0x3f800000,
0x3dc9bf80,0x3f7f0000,0x3f46bf35,0x3f223f35,0xbe953f7b,0xbf75be48,0xbf623f0e,0xbef1bf55,0x3ef1bf6d,0x3f623ec4,0x3f75bec4,0x3e953f6d,
0xbf223f55,0xbf46bf0e,0xbf7f3e48,0xbdc9bf7b,0xbe483f80,0xbf7b0000,0xbf7b0000,0x3e48bf80,0x3f0ebf6d,0x3f553ec4,0x3f553ec4,0xbf0e3f6d,
0xbf553f35,0xbf0ebf35,0xbf0ebf35,0x3f55bf35,0x3f7bbec4,0x3e483f6d,0x3e483f6d,0xbf7b3ec4,0x3e95bf80,0x3f750000,0x3ef13f35,0xbf623f35,
0xbf463f55,0xbf22bf0e,0x3dc9bf7b,0x3f7fbe48,0x3f7fbec4,0x3dc93f6d,0xbf223f6d,0xbf46bec4,0xbf62be48,0x3ef1bf7b,0x3f75bf0e,0x3e953f55,
0xbec43f80,0xbf6d0000,0x3ec4bf80,0x3f6d0000,0x3f6dbf35,0x3ec43f35,0xbf6d3f35,0xbec4bf35,0xbf6d0000,0x3ec4bf80,0x3f6d0000,0xbec43f80,
0x3ec43f35,0xbf6d3f35,0xbec4bf35,0x3f6dbf35,0x3ef1bf80,0x3f620000,0xbf753f35,0xbe95bf35,0xbf7f3f0e,0xbdc9bf55,0x3f463e48,0xbf223f7b,
0x3f223ec4,0xbf463f6d,0x3dc9bf6d,0x3f7fbec4,0x3e95bf7b,0x3f75be48,0xbf623f55,0xbef1bf0e,0xbf0e3f80,0xbf550000,0x3f550000,0xbf0e3f80,
0x3f7bbec4,0xbe483f6d,0x3e48bf6d,0x3f7bbec4,0xbe48bf35,0x3f7bbf35,0xbf7b3f35,0xbe48bf35,0xbf553f6d,0xbf0ebec4,0x3f0e3ec4,0xbf553f6d,
0x3f22bf80,0x3f460000,0xbdc9bf35,0x3f7fbf35,0xbf623e48,0x3ef1bf7b,0xbf753f55,0xbe95bf0e,0xbe953f6d,0xbf753ec4,0x3ef13ec4,0xbf623f6d,
0x3f7fbf0e,0xbdc93f55,0x3f46bf7b,0x3f223e48,0xbf353f80,0xbf350000,0xbf353f80,0xbf350000,0x3f350000,0xbf353f80,0x3f350000,0xbf353f80,
0x3f35bf80,0x3f350000,0x3f35bf80,0x3f350000,0xbf350000,0x3f35bf80,0xbf350000,0x3f35bf80,0x3f46bf80,0x3f220000,0x3f7fbf35,0xbdc93f35,
0xbef1be48,0x3f62bf7b,0x3e95bf55,0x3f75bf0e,0xbf753f6d,0xbe95bec4,0xbf623ec4,0x3ef1bf6d,0x3dc93f0e,0xbf7f3f55,0xbf223f7b,0xbf463e48,
0xbf553f80,0xbf0e0000,0xbf0e0000,0x3f55bf80,0x3e483ec4,0xbf7b3f6d,0xbf7b3f6d,0xbe48bec4,0x3f7bbf35,0xbe483f35,0xbe483f35,0xbf7b3f35,
0x3f0ebf6d,0x3f55bec4,0x3f55bec4,0xbf0e3f6d,0x3f62bf80,0x3ef10000,0xbe953f35,0xbf753f35,0x3dc9bf0e,0x3f7fbf55,0x3f22be48,0xbf463f7b,
0xbf463ec4,0x3f22bf6d,0x3f7fbf6d,0x3dc93ec4,0xbf753f7b,0xbe95be48,0x3ef1bf55,0x3f62bf0e,0xbf6d3f80,0xbec40000,0x3f6dbf80,0x3ec40000,
0xbec43f35,0xbf6d3f35,0x3ec4bf35,0x3f6dbf35,0x3ec40000,0xbf6d3f80,0xbec40000,0x3f6dbf80,0x3f6dbf35,0xbec43f35,0xbf6d3f35,0x3ec4bf35,
0x3f75bf80,0x3e950000,0xbf623f35,0x3ef1bf35,0x3f22bf55,0x3f46bf0e,0xbf7f3f7b,0xbdc9be48,0x3dc9bec4,0x3f7fbf6d,0xbf463f6d,0xbf223ec4,
0xbef13e48,0x3f62bf7b,0xbe953f0e,0xbf753f55,0xbf7b3f80,0xbe480000,0x3e480000,0xbf7b3f80,0xbf553f6d,0xbf0e3ec4,0x3f0ebec4,0xbf553f6d,
0xbf0e3f35,0xbf553f35,0x3f55bf35,0xbf0e3f35,0xbe483ec4,0xbf7b3f6d,0x3f7bbf6d,0xbe483ec4,0x3f7fbf80,0x3dc90000,0x3f22bf35,0x3f46bf35,
0x3f75bf7b,0x3e95be48,0x3ef1bf0e,0x3f62bf55,0x3f62bf6d,0x3ef1bec4,0x3e95bec4,0x3f75bf6d,0x3f46bf55,0x3f22bf0e,0x3dc9be48,0x3f7fbf7b,
0x3f803f80,0xbf803f80,0x3f803f80,0xbf803f80,0x3f803f80,0xbf803f80,0x3f803f80,0xbf803f80,0x3f803f80,0xbf803f80,0x3f803f80,0xbf803f80,
0x3f803f80,0xbf803f80,0x3f803f80,0xbf803f80,0x3dc90000,0x3f7f3f80,0x3f463f35,0x3f223f35,0x3e953e48,0x3f753f7b,0x3f623f55,0x3ef13f0e,
0x3ef13ec4,0x3f623f6d,0x3f753f6d,0x3e953ec4,0x3f223f0e,0x3f463f55,0x3f7f3f7b,0x3dc93e48,0xbf7bbf80,0x3e480000,0x3e480000,0x3f7b3f80,
0xbf55bf6d,0x3f0e3ec4,0x3f0e3ec4,0x3f553f6d,0xbf0ebf35,0x3f553f35,0x3f553f35,0x3f0e3f35,0xbe48bec4,0x3f7b3f6d,0x3f7b3f6d,0x3e483ec4,
0xbe950000,0xbf75bf80,0xbef1bf35,0x3f623f35,0xbf46bf0e,0xbf22bf55,0x3dc9be48,0x3f7f3f7b,0xbf7fbf6d,0xbdc9bec4,0x3f223ec4,0x3f463f6d,
0xbf62bf7b,0x3ef13e48,0x3f753f55,0x3e953f0e,0x3f6d3f80,0xbec40000,0xbf6dbf80,0x3ec40000,0x3ec43f35,0xbf6dbf35,0xbec4bf35,0x3f6d3f35,
0xbec40000,0xbf6dbf80,0x3ec40000,0x3f6d3f80,0xbf6dbf35,0xbec4bf35,0x3f6d3f35,0x3ec43f35,0x3ef10000,0x3f623f80,0xbf75bf35,0xbe95bf35,
0x3f7f3f55,0x3dc93f0e,0xbf46bf7b,0x3f223e48,0x3f223f6d,0xbf46bec4,0x3dc9bec4,0x3f7f3f6d,0xbe953e48,0xbf75bf7b,0x3f623f0e,0x3ef13f55,
0xbf55bf80,0x3f0e0000,0xbf0e0000,0xbf55bf80,0x3e48bec4,0x3f7b3f6d,0xbf7bbf6d,0x3e48bec4,0x3f7b3f35,0x3e483f35,0xbe48bf35,0x3f7b3f35,
0x3f0e3f6d,0xbf55bec4,0x3f553ec4,0x3f0e3f6d,0xbf220000,0xbf46bf80,0x3dc93f35,0xbf7fbf35,0xbf62bf7b,0x3ef1be48,0xbf75bf0e,0xbe95bf55,
0x3e95bec4,0x3f753f6d,0xbef1bf6d,0x3f623ec4,0x3f7f3f55,0xbdc93f0e,0x3f463e48,0x3f223f7b,0x3f353f80,0xbf350000,0x3f353f80,0xbf350000,
0xbf350000,0xbf35bf80,0xbf350000,0xbf35bf80,0xbf35bf80,0x3f350000,0xbf35bf80,0x3f350000,0x3f350000,0x3f353f80,0x3f350000,0x3f353f80,
0x3f460000,0x3f223f80,0x3f7f3f35,0xbdc93f35,0x3ef13f7b,0xbf62be48,0xbe953f0e,0xbf75bf55,0xbf75bec4,0xbe95bf6d,0xbf62bf6d,0x3ef1bec4,
0xbdc9bf55,0x3f7f3f0e,0x3f22be48,0x3f463f7b,0xbf0ebf80,0x3f550000,0x3f550000,0x3f0e3f80,0x3f7b3ec4,0x3e483f6d,0x3e483f6d,0xbf7bbec4,
0xbe483f35,0xbf7bbf35,0xbf7bbf35,0x3e48bf35,0xbf55bf6d,0x3f0ebec4,0x3f0ebec4,0x3f553f6d,0xbf620000,0xbef1bf80,0x3e95bf35,0x3f753f35,
0x3dc9bf55,0x3f7f3f0e,0x3f223f7b,0xbf463e48,0x3f463f6d,0xbf223ec4,0xbf7fbec4,0xbdc9bf6d,0xbf75be48,0xbe95bf7b,0x3ef1bf0e,0x3f623f55,
0x3ec43f80,0xbf6d0000,0xbec4bf80,0x3f6d0000,0xbf6dbf35,0x3ec4bf35,0x3f6d3f35,0xbec43f35,0x3f6d0000,0x3ec43f80,0xbf6d0000,0xbec4bf80,
0xbec43f35,0xbf6dbf35,0x3ec4bf35,0x3f6d3f35,0x3f750000,0x3e953f80,0xbf62bf35,0x3ef1bf35,0xbf223f0e,0xbf46bf55,0x3f7f3e48,0x3dc93f7b,
0x3dc9bf6d,0x3f7f3ec4,0xbf463ec4,0xbf22bf6d,0x3ef13f7b,0xbf623e48,0x3e95bf55,0x3f753f0e,0xbe48bf80,0x3f7b0000,0xbf7b0000,0xbe48bf80,
0x3f0e3f6d,0xbf553ec4,0x3f55bec4,0x3f0e3f6d,0xbf55bf35,0x3f0ebf35,0xbf0e3f35,0xbf55bf35,0x3f7b3ec4,0xbe483f6d,0x3e48bf6d,0x3f7b3ec4,
0xbf7f0000,0xbdc9bf80,0xbf223f35,0xbf46bf35,0x3f75be48,0x3e953f7b,0x3ef1bf55,0x3f623f0e,0xbf623ec4,0xbef1bf6d,0xbe953f6d,0xbf75bec4,
0x3f46bf0e,0x3f223f55,0x3dc9bf7b,0x3f7f3e48,0x3f80,0xbf800000,0x3f80,0xbf800000,0xbf80,0x3f800000,0xbf80,0x3f800000,
0x3f80,0xbf800000,0x3f80,0xbf800000,0xbf80,0x3f800000,0xbf80,0x3f800000,0x3f7f0000,0xbdc93f80,0x3f223f35,0xbf463f35,
0xbf75be48,0x3e95bf7b,0xbef1bf55,0x3f62bf0e,0x3f623ec4,0xbef13f6d,0x3e953f6d,0xbf753ec4,0xbf46bf0e,0x3f22bf55,0xbdc9bf7b,0x3f7fbe48,
0x3e48bf80,0x3f7b0000,0x3f7b0000,0xbe483f80,0xbf0e3f6d,0xbf55bec4,0xbf55bec4,0x3f0ebf6d,0x3f55bf35,0x3f0e3f35,0x3f0e3f35,0xbf553f35,
0xbf7b3ec4,0xbe48bf6d,0xbe48bf6d,0x3f7bbec4,0xbf750000,0x3e95bf80,0x3f62bf35,0x3ef13f35,0x3f223f0e,0xbf463f55,0xbf7f3e48,0x3dc9bf7b,
0xbdc9bf6d,0x3f7fbec4,0x3f463ec4,0xbf223f6d,0xbef13f7b,0xbf62be48,0xbe95bf55,0x3f75bf0e,0xbec43f80,0xbf6d0000,0x3ec4bf80,0x3f6d0000,
0x3f6dbf35,0x3ec43f35,0xbf6d3f35,0xbec4bf35,0xbf6d0000,0x3ec4bf80,0x3f6d0000,0xbec43f80,0x3ec43f35,0xbf6d3f35,0xbec4bf35,0x3f6dbf35,
0x3f620000,0xbef13f80,0xbe95bf35,0x3f75bf35,0xbdc9bf55,0x3f7fbf0e,0xbf223f7b,0xbf46be48,0xbf463f6d,0xbf22bec4,0x3f7fbec4,0xbdc93f6d,
0x3f75be48,0xbe953f7b,0xbef1bf0e,0x3f62bf55,0x3f0ebf80,0x3f550000,0xbf550000,0x3f0ebf80,0xbf7b3ec4,0x3e48bf6d,0xbe483f6d,0xbf7b3ec4,
0x3e483f35,0xbf7b3f35,0x3f7bbf35,0x3e483f35,0x3f55bf6d,0x3f0e3ec4,0xbf0ebec4,0x3f55bf6d,0xbf460000,0x3f22bf80,0xbf7f3f35,0xbdc9bf35,
0xbef13f7b,0xbf623e48,0x3e953f0e,0xbf753f55,0x3f75bec4,0xbe953f6d,0x3f62bf6d,0x3ef13ec4,0x3dc9bf55,0x3f7fbf0e,0xbf22be48,0x3f46bf7b,
0xbf353f80,0xbf350000,0xbf353f80,0xbf350000,0x3f350000,0xbf353f80,0x3f350000,0xbf353f80,0x3f35bf80,0x3f350000,0x3f35bf80,0x3f350000,
0xbf350000,0x3f35bf80,0xbf350000,0x3f35bf80,0x3f220000,0xbf463f80,0xbdc93f35,0xbf7f3f35,0x3f62bf7b,0x3ef13e48,0x3f75bf0e,0xbe953f55,
0xbe95bec4,0x3f75bf6d,0x3ef1bf6d,0x3f62bec4,0xbf7f3f55,0xbdc9bf0e,0xbf463e48,0x3f22bf7b,0x3f55bf80,0x3f0e0000,0x3f0e0000,0xbf553f80,
0xbe48bec4,0x3f7bbf6d,0x3f7bbf6d,0x3e483ec4,0xbf7b3f35,0x3e48bf35,0x3e48bf35,0x3f7bbf35,0xbf0e3f6d,0xbf553ec4,0xbf553ec4,0x3f0ebf6d,
0xbef10000,0x3f62bf80,0x3f75bf35,0xbe953f35,0xbf7f3f55,0x3dc9bf0e,0x3f46bf7b,0x3f22be48,0xbf223f6d,0xbf463ec4,0xbdc9bec4,0x3f7fbf6d,
0x3e953e48,0xbf753f7b,0xbf623f0e,0x3ef1bf55,0xbf6d3f80,0xbec40000,0x3f6dbf80,0x3ec40000,0xbec43f35,0xbf6d3f35,0x3ec4bf35,0x3f6dbf35,
0x3ec40000,0xbf6d3f80,0xbec40000,0x3f6dbf80,0x3f6dbf35,0xbec43f35,0xbf6d3f35,0x3ec4bf35,0x3e950000,0xbf753f80,0x3ef1bf35,0x3f62bf35,
0x3f46bf0e,0xbf223f55,0xbdc9be48,0x3f7fbf7b,0x3f7fbf6d,0xbdc93ec4,0xbf223ec4,0x3f46bf6d,0x3f62bf7b,0x3ef1be48,0xbf753f55,0x3e95bf0e,
0x3f7bbf80,0x3e480000,0xbe480000,0x3f7bbf80,0x3f55bf6d,0x3f0ebec4,0xbf0e3ec4,0x3f55bf6d,0x3f0ebf35,0x3f55bf35,0xbf553f35,0x3f0ebf35,
0x3e48bec4,0x3f7bbf6d,0xbf7b3f6d,0x3e48bec4,0xbdc90000,0x3f7fbf80,0xbf463f35,0x3f22bf35,0xbe953e48,0x3f75bf7b,0xbf623f55,0x3ef1bf0e,
0xbef13ec4,0x3f62bf6d,0xbf753f6d,0x3e95bec4,0xbf223f0e,0x3f46bf55,0xbf7f3f7b,0x3dc9be48,0x40003f80,0x3fb53f80,0x3f80,0xbfb53f80,
0x40004000,0xbfb50000,0x0,0xbfb5c000,0x40004000,0xbfb5c000,0x0,0x3fb50000,0x40004000,0x3fb50000,0x0,0x3fb54000,
0x3fff3f80,0x3fa23f80,0xbe49bf80,0xbfc6bf80,0x3ff53ffb,0xbfe2bec8,0xbf15bec8,0xbf71bffb,0x3fe23fed,0xbf15bfed,0xbf71bf44,0x3ff53f44,
0x3fc63fd5,0x3fff3f8e,0xbfa2bf8e,0x3e493fd5,0x3ffb3f80,0x3f8e3f80,0xbec83f80,0xbfd53f80,0x3fd53fed,0xbffbbf44,0xbf8ebf44,0xbec8bfed,
0x3f8e3fb5,0x3ec8bfb5,0xbfd5bfb5,0x3ffb3fb5,0x3ec83f44,0x3fd53fed,0xbffbbfed,0xbf8e3f44,0x3ff53f80,0x3f713f80,0xbf15bf80,0xbfe2bf80,
0x3fa23fd5,0xbfffbf8e,0xbfc6bf8e,0x3e49bfd5,0x3e493f44,0x3fa2bf44,0xbfffbfed,0x3fc63fed,0xbf71bec8,0x3f153ffb,0xbfe2bffb,0xbff5bec8,
0x3fed3f80,0x3f443f80,0xbf443f80,0xbfed3f80,0x3f443fb5,0xbfedbfb5,0xbfedbfb5,0x3f44bfb5,0xbf440000,0x3fed0000,0xbfedc000,0x3f444000,
0xbfedbfb5,0xbf443fb5,0xbf44bfb5,0xbfedbfb5,0x3fe23f80,0x3f153f80,0xbf71bf80,0xbff5bf80,0x3e493f8e,0xbfc6bfd5,0xbfffbfd5,0x3fa2bf8e,
0xbfc6bf44,0x3fff3f44,0xbfa2bfed,0xbe493fed,0xbff5bffb,0xbfe23ec8,0x3f15bec8,0xbf71bffb,0x3fd53f80,0x3ec83f80,0xbf8e3f80,0xbffb3f80,
0xbec83f44,0xbf8ebfed,0xbffbbfed,0x3fd5bf44,0xbffbbfb5,0x3fd53fb5,0xbec8bfb5,0xbf8e3fb5,0xbf8ebfed,0xbffbbf44,0x3fd53f44,0x3ec8bfed,
0x3fc63f80,0x3e493f80,0xbfa2bf80,0xbfffbf80,0xbf713ec8,0xbf15bffb,0xbfe2bffb,0x3ff5bec8,0xbff5bfed,0x3f713fed,0x3f15bf44,0xbfe23f44,
0x3e49bf8e,0xbfa2bfd5,0x3fff3fd5,0x3fc6bf8e,0x3f80,0xbfb53f80,0xc0003f80,0xbfb53f80,0xc000,0x3fb50000,0x40000000,0xbfb54000,
0x4000,0x3fb5c000,0xc0000000,0x3fb50000,0xc000,0xbfb50000,0x40000000,0x3fb5c000,0xbe493f80,0xbfc63f80,0xbfffbf80,0xbfa2bf80,
0x3f15bffb,0x3f713ec8,0x3ff53ec8,0xbfe23ffb,0xbf713fed,0x3ff5bfed,0xbfe2bf44,0x3f153f44,0x3fa2bfd5,0xbe49bf8e,0x3fc63f8e,0x3fffbfd5,
0xbec83f80,0xbfd53f80,0xbffb3f80,0xbf8e3f80,0x3f8ebfed,0x3ec83f44,0x3fd53f44,0xbffb3fed,0xbfd53fb5,0x3ffbbfb5,0xbf8ebfb5,0xbec83fb5,
0x3ffbbf44,0x3f8ebfed,0x3ec83fed,0x3fd5bf44,0xbf153f80,0xbfe23f80,0xbff5bf80,0xbf71bf80,0x3fc6bfd5,0xbe493f8e,0x3fa23f8e,0xbfff3fd5,
0xbfff3f44,0x3fc6bf44,0xbe49bfed,0xbfa23fed,0x3fe23ec8,0x3ff5bffb,0xbf713ffb,0x3f153ec8,0xbf443f80,0xbfed3f80,0xbfed3f80,0xbf443f80,
0x3fedbfb5,0xbf443fb5,0x3f443fb5,0xbfed3fb5,0xbfed0000,0x3f440000,0x3f44c000,0xbfed4000,0x3f443fb5,0x3fedbfb5,0xbfed3fb5,0xbf443fb5,
0xbf713f80,0xbff53f80,0xbfe2bf80,0xbf15bf80,0x3fffbf8e,0xbfa23fd5,0x3e493fd5,0xbfc63f8e,0xbfa2bf44,0xbe493f44,0x3fc6bfed,0xbfff3fed,
0xbf153ffb,0x3f71bec8,0xbff53ec8,0xbfe23ffb,0xbf8e3f80,0xbffb3f80,0xbfd53f80,0xbec83f80,0x3ffbbf44,0xbfd53fed,0xbec83fed,0xbf8e3f44,
0xbec8bfb5,0xbf8e3fb5,0x3ffbbfb5,0xbfd53fb5,0xbfd53fed,0xbec83f44,0xbf8ebf44,0xbffb3fed,0xbfa23f80,0xbfff3f80,0xbfc6bf80,0xbe49bf80,
0x3fe2bec8,0xbff53ffb,0xbf713ffb,0xbf153ec8,0x3f15bfed,0xbfe23fed,0x3ff5bf44,0xbf713f44,0xbfff3f8e,0xbfc63fd5,0x3e49bfd5,0xbfa23f8e,
0xc0003f80,0xbfb53f80,0x3f80,0x3fb53f80,0xc0004000,0x3fb50000,0x0,0x3fb5c000,0xc0004000,0x3fb5c000,0x0,0xbfb50000,
0xc0004000,0xbfb50000,0x0,0xbfb54000,0xbfff3f80,0xbfa23f80,0x3e49bf80,0x3fc6bf80,0xbff53ffb,0x3fe2bec8,0x3f15bec8,0x3f71bffb,
0xbfe23fed,0x3f15bfed,0x3f71bf44,0xbff53f44,0xbfc63fd5,0xbfff3f8e,0x3fa2bf8e,0xbe493fd5,0xbffb3f80,0xbf8e3f80,0x3ec83f80,0x3fd53f80,
0xbfd53fed,0x3ffbbf44,0x3f8ebf44,0x3ec8bfed,0xbf8e3fb5,0xbec8bfb5,0x3fd5bfb5,0xbffb3fb5,0xbec83f44,0xbfd53fed,0x3ffbbfed,0x3f8e3f44,
0xbff53f80,0xbf713f80,0x3f15bf80,0x3fe2bf80,0xbfa23fd5,0x3fffbf8e,0x3fc6bf8e,0xbe49bfd5,0xbe493f44,0xbfa2bf44,0x3fffbfed,0xbfc63fed,
0x3f71bec8,0xbf153ffb,0x3fe2bffb,0x3ff5bec8,0xbfed3f80,0xbf443f80,0x3f443f80,0x3fed3f80,0xbf443fb5,0x3fedbfb5,0x3fedbfb5,0xbf44bfb5,
0x3f440000,0xbfed0000,0x3fedc000,0xbf444000,0x3fedbfb5,0x3f443fb5,0x3f44bfb5,0x3fedbfb5,0xbfe23f80,0xbf153f80,0x3f71bf80,0x3ff5bf80,
0xbe493f8e,0x3fc6bfd5,0x3fffbfd5,0xbfa2bf8e,0x3fc6bf44,0xbfff3f44,0x3fa2bfed,0x3e493fed,0x3ff5bffb,0x3fe23ec8,0xbf15bec8,0x3f71bffb,
0xbfd53f80,0xbec83f80,0x3f8e3f80,0x3ffb3f80,0x3ec83f44,0x3f8ebfed,0x3ffbbfed,0xbfd5bf44,0x3ffbbfb5,0xbfd53fb5,0x3ec8bfb5,0x3f8e3fb5,
0x3f8ebfed,0x3ffbbf44,0xbfd53f44,0xbec8bfed,0xbfc63f80,0xbe493f80,0x3fa2bf80,0x3fffbf80,0x3f713ec8,0x3f15bffb,0x3fe2bffb,0xbff5bec8,
0x3ff5bfed,0xbf713fed,0xbf15bf44,0x3fe23f44,0xbe49bf8e,0x3fa2bfd5,0xbfff3fd5,0xbfc6bf8e,0x3f80,0x3fb53f80,0x40003f80,0x3fb53f80,
0xc000,0xbfb50000,0xc0000000,0x3fb54000,0x4000,0xbfb5c000,0x40000000,0xbfb50000,0xc000,0x3fb50000,0xc0000000,0xbfb5c000,
0x3e493f80,0x3fc63f80,0x3fffbf80,0x3fa2bf80,0xbf15bffb,0xbf713ec8,0xbff53ec8,0x3fe23ffb,0x3f713fed,0xbff5bfed,0x3fe2bf44,0xbf153f44,
0xbfa2bfd5,0x3e49bf8e,0xbfc63f8e,0xbfffbfd5,0x3ec83f80,0x3fd53f80,0x3ffb3f80,0x3f8e3f80,0xbf8ebfed,0xbec83f44,0xbfd53f44,0x3ffb3fed,
0x3fd53fb5,0xbffbbfb5,0x3f8ebfb5,0x3ec83fb5,0xbffbbf44,0xbf8ebfed,0xbec83fed,0xbfd5bf44,0x3f153f80,0x3fe23f80,0x3ff5bf80,0x3f71bf80,
0xbfc6bfd5,0x3e493f8e,0xbfa23f8e,0x3fff3fd5,0x3fff3f44,0xbfc6bf44,0x3e49bfed,0x3fa23fed,0xbfe23ec8,0xbff5bffb,0x3f713ffb,0xbf153ec8,
0x3f443f80,0x3fed3f80,0x3fed3f80,0x3f443f80,0xbfedbfb5,0x3f443fb5,0xbf443fb5,0x3fed3fb5,0x3fed0000,0xbf440000,0xbf44c000,0x3fed4000,
0xbf443fb5,0xbfedbfb5,0x3fed3fb5,0x3f443fb5,0x3f713f80,0x3ff53f80,0x3fe2bf80,0x3f15bf80,0xbfffbf8e,0x3fa23fd5,0xbe493fd5,0x3fc63f8e,
0x3fa2bf44,0x3e493f44,0xbfc6bfed,0x3fff3fed,0x3f153ffb,0xbf71bec8,0x3ff53ec8,0x3fe23ffb,0x3f8e3f80,0x3ffb3f80,0x3fd53f80,0x3ec83f80,
0xbffbbf44,0x3fd53fed,0x3ec83fed,0x3f8e3f44,0x3ec8bfb5,0x3f8e3fb5,0xbffbbfb5,0x3fd53fb5,0x3fd53fed,0x3ec83f44,0x3f8ebf44,0x3ffb3fed,
0x3fa23f80,0x3fff3f80,0x3fc6bf80,0x3e49bf80,0xbfe2bec8,0x3ff53ffb,0x3f713ffb,0x3f153ec8,0xbf15bfed,0x3fe23fed,0xbff5bf44,0x3f713f44,
0x3fff3f8e,0x3fc63fd5,0xbe49bfd5,0x3fa23f8e,0x40004000,0x3fb54000,0x0,0xbfb50000,0x40004000,0xbfb50000,0x0,0xbfb5c000,
0x40004000,0xbfb5c000,0x0,0x3fb50000,0x40004000,0x3fb50000,0x0,0x3fb54000,0x3fa23fb5,0xbe493fb5,0xbfc6bfb5,0xbfffbfb5,
0x3f713f8e,0xbff5bfd5,0xbfe2bfd5,0x3f15bf8e,0x3f153f44,0x3f71bf44,0xbff5bfed,0x3fe23fed,0x3e493ec8,0x3fc63ffb,0xbfffbffb,0xbfa23ec8,
0xbec80000,0xbfd50000,0xbffbc000,0xbf8ec000,0xbf8ebf44,0xbec8bfed,0xbfd5bfed,0x3ffb3f44,0xbfd5bfb5,0x3ffb3fb5,0xbf8ebfb5,0xbec83fb5,
0xbffbbfed,0xbf8e3f44,0xbec8bf44,0xbfd5bfed,0xbfe2bfb5,0xbff5bfb5,0xbf71bfb5,0x3f15bfb5,0xbfffbffb,0x3fc6bec8,0x3e49bec8,0x3fa23ffb,
0xbfc6bfed,0x3e493fed,0x3fa23f44,0xbfffbf44,0xbf15bf8e,0xbfe2bfd5,0x3ff53fd5,0x3f71bf8e,0xbfedc000,0xbf44c000,0x3f440000,0x3fed0000,
0xbf44bfb5,0x3fed3fb5,0x3fed3fb5,0xbf443fb5,0x3f440000,0xbfed0000,0x3fed4000,0xbf44c000,0x3fed3fb5,0x3f44bfb5,0x3f443fb5,0x3fed3fb5,
0xbf15bfb5,0x3f71bfb5,0x3ff53fb5,0x3fe23fb5,0x3fa23ec8,0x3e493ffb,0x3fc63ffb,0xbfffbec8,0x3fff3fed,0xbfa2bfed,0xbe493f44,0x3fc6bf44,
0x3f713fd5,0x3ff53f8e,0xbfe2bf8e,0xbf153fd5,0x3f8e0000,0x3ffb0000,0x3fd54000,0x3ec84000,0x3ffb3fed,0xbfd53f44,0xbec83f44,0xbf8ebfed,
0x3ec83fb5,0x3f8ebfb5,0xbffbbfb5,0x3fd53fb5,0xbfd5bf44,0xbec83fed,0xbf8ebfed,0xbffbbf44,0x3fff3fb5,0x3fc63fb5,0x3e493fb5,0xbfa23fb5,
0x3f153fd5,0xbfe2bf8e,0xbff5bf8e,0x3f71bfd5,0xbfe2bf44,0x3ff53f44,0xbf71bfed,0xbf153fed,0xbfa2bffb,0xbfffbec8,0x3fc63ec8,0x3e49bffb,
0x4000,0xbfb54000,0xc0000000,0xbfb50000,0xc000,0x3fb50000,0x40000000,0xbfb54000,0x4000,0x3fb5c000,0xc0000000,0x3fb50000,
0xc000,0xbfb50000,0x40000000,0x3fb5c000,0xbfc63fb5,0xbfff3fb5,0xbfa2bfb5,0x3e49bfb5,0x3fe2bf8e,0xbf153fd5,0x3f713fd5,0xbff53f8e,
0xbff53f44,0x3fe2bf44,0xbf15bfed,0xbf713fed,0x3fffbec8,0x3fa2bffb,0x3e493ffb,0x3fc6bec8,0xbffb0000,0xbf8e0000,0x3ec8c000,0x3fd5c000,
0x3fd53f44,0xbffb3fed,0xbf8e3fed,0xbec8bf44,0xbf8ebfb5,0xbec83fb5,0x3fd5bfb5,0xbffb3fb5,0x3ec83fed,0x3fd5bf44,0xbffb3f44,0xbf8e3fed,
0xbf71bfb5,0x3f15bfb5,0x3fe2bfb5,0x3ff5bfb5,0xbe493ffb,0xbfa23ec8,0xbfff3ec8,0x3fc6bffb,0x3fa2bfed,0xbfff3fed,0x3fc63f44,0xbe49bf44,
0xbff53f8e,0xbf713fd5,0xbf15bfd5,0xbfe23f8e,0x3f44c000,0x3fedc000,0x3fed0000,0x3f440000,0xbfed3fb5,0x3f44bfb5,0xbf44bfb5,0x3fedbfb5,
0x3fed0000,0xbf440000,0xbf444000,0x3fedc000,0xbf44bfb5,0xbfed3fb5,0x3fedbfb5,0x3f44bfb5,0x3ff5bfb5,0x3fe2bfb5,0x3f153fb5,0xbf713fb5,
0xbfc6bec8,0x3fffbffb,0x3fa2bffb,0x3e493ec8,0xbe493fed,0x3fc6bfed,0xbfff3f44,0x3fa2bf44,0x3fe2bfd5,0x3f15bf8e,0x3f713f8e,0x3ff5bfd5,
0x3fd50000,0x3ec80000,0xbf8e4000,0xbffb4000,0x3ec8bfed,0x3f8ebf44,0x3ffbbf44,0xbfd53fed,0xbffb3fb5,0x3fd5bfb5,0xbec8bfb5,0xbf8e3fb5,
0x3f8e3f44,0x3ffbbfed,0xbfd53fed,0xbec83f44,0x3e493fb5,0xbfa23fb5,0xbfff3fb5,0xbfc63fb5,0x3ff5bfd5,0xbf713f8e,0x3f153f8e,0xbfe23fd5,
0xbf71bf44,0xbf153f44,0x3fe2bfed,0xbff53fed,0xbfc63ffb,0xbe493ec8,0xbfa2bec8,0xbfff3ffb,0xc0004000,0xbfb54000,0x0,0x3fb50000,
0xc0004000,0x3fb50000,0x0,0x3fb5c000,0xc0004000,0x3fb5c000,0x0,0xbfb50000,0xc0004000,0xbfb50000,0x0,0xbfb54000,
0xbfa23fb5,0x3e493fb5,0x3fc6bfb5,0x3fffbfb5,0xbf713f8e,0x3ff5bfd5,0x3fe2bfd5,0xbf15bf8e,0xbf153f44,0xbf71bf44,0x3ff5bfed,0xbfe23fed,
0xbe493ec8,0xbfc63ffb,0x3fffbffb,0x3fa23ec8,0x3ec80000,0x3fd50000,0x3ffbc000,0x3f8ec000,0x3f8ebf44,0x3ec8bfed,0x3fd5bfed,0xbffb3f44,
0x3fd5bfb5,0xbffb3fb5,0x3f8ebfb5,0x3ec83fb5,0x3ffbbfed,0x3f8e3f44,0x3ec8bf44,0x3fd5bfed,0x3fe2bfb5,0x3ff5bfb5,0x3f71bfb5,0xbf15bfb5,
0x3fffbffb,0xbfc6bec8,0xbe49bec8,0xbfa23ffb,0x3fc6bfed,0xbe493fed,0xbfa23f44,0x3fffbf44,0x3f15bf8e,0x3fe2bfd5,0xbff53fd5,0xbf71bf8e,
0x3fedc000,0x3f44c000,0xbf440000,0xbfed0000,0x3f44bfb5,0xbfed3fb5,0xbfed3fb5,0x3f443fb5,0xbf440000,0x3fed0000,0xbfed4000,0x3f44c000,
0xbfed3fb5,0xbf44bfb5,0xbf443fb5,0xbfed3fb5,0x3f15bfb5,0xbf71bfb5,0xbff53fb5,0xbfe23fb5,0xbfa23ec8,0xbe493ffb,0xbfc63ffb,0x3fffbec8,
0xbfff3fed,0x3fa2bfed,0x3e493f44,0xbfc6bf44,0xbf713fd5,0xbff53f8e,0x3fe2bf8e,0x3f153fd5,0xbf8e0000,0xbffb0000,0xbfd54000,0xbec84000,
0xbffb3fed,0x3fd53f44,0x3ec83f44,0x3f8ebfed,0xbec83fb5,0xbf8ebfb5,0x3ffbbfb5,0xbfd53fb5,0x3fd5bf44,0x3ec83fed,0x3f8ebfed,0x3ffbbf44,
0xbfff3fb5,0xbfc63fb5,0xbe493fb5,0x3fa23fb5,0xbf153fd5,0x3fe2bf8e,0x3ff5bf8e,0xbf71bfd5,0x3fe2bf44,0xbff53f44,0x3f71bfed,0x3f153fed,
0x3fa2bffb,0x3fffbec8,0xbfc63ec8,0xbe49bffb,0x4000,0x3fb54000,0x40000000,0x3fb50000,0xc000,0xbfb50000,0xc0000000,0x3fb54000,
0x4000,0xbfb5c000,0x40000000,0xbfb50000,0xc000,0x3fb50000,0xc0000000,0xbfb5c000,0x3fc63fb5,0x3fff3fb5,0x3fa2bfb5,0xbe49bfb5,
0xbfe2bf8e,0x3f153fd5,0xbf713fd5,0x3ff53f8e,0x3ff53f44,0xbfe2bf44,0x3f15bfed,0x3f713fed,0xbfffbec8,0xbfa2bffb,0xbe493ffb,0xbfc6bec8,
0x3ffb0000,0x3f8e0000,0xbec8c000,0xbfd5c000,0xbfd53f44,0x3ffb3fed,0x3f8e3fed,0x3ec8bf44,0x3f8ebfb5,0x3ec83fb5,0xbfd5bfb5,0x3ffb3fb5,
0xbec83fed,0xbfd5bf44,0x3ffb3f44,0x3f8e3fed,0x3f71bfb5,0xbf15bfb5,0xbfe2bfb5,0xbff5bfb5,0x3e493ffb,0x3fa23ec8,0x3fff3ec8,0xbfc6bffb,
0xbfa2bfed,0x3fff3fed,0xbfc63f44,0x3e49bf44,0x3ff53f8e,0x3f713fd5,0x3f15bfd5,0x3fe23f8e,0xbf44c000,0xbfedc000,0xbfed0000,0xbf440000,
0x3fed3fb5,0xbf44bfb5,0x3f44bfb5,0xbfedbfb5,0xbfed0000,0x3f440000,0x3f444000,0xbfedc000,0x3f44bfb5,0x3fed3fb5,0xbfedbfb5,0xbf44bfb5,
0xbff5bfb5,0xbfe2bfb5,0xbf153fb5,0x3f713fb5,0x3fc6bec8,0xbfffbffb,0xbfa2bffb,0xbe493ec8,0x3e493fed,0xbfc6bfed,0x3fff3f44,0xbfa2bf44,
0xbfe2bfd5,0xbf15bf8e,0xbf713f8e,0xbff5bfd5,0xbfd50000,0xbec80000,0x3f8e4000,0x3ffb4000,0xbec8bfed,0xbf8ebf44,0xbffbbf44,0x3fd53fed,
0x3ffb3fb5,0xbfd5bfb5,0x3ec8bfb5,0x3f8e3fb5,0xbf8e3f44,0xbffbbfed,0x3fd53fed,0x3ec83f44,0xbe493fb5,0x3fa23fb5,0x3fff3fb5,0x3fc63fb5,
0xbff5bfd5,0x3f713f8e,0xbf153f8e,0x3fe23fd5,0x3f71bf44,0x3f153f44,0xbfe2bfed,0x3ff53fed,0x3fc63ffb,0x3e493ec8,0x3fa2bec8,0x3fff3ffb,
0x40004000,0x3fb54000,0x0,0xbfb50000,0x40004000,0xbfb50000,0x0,0xbfb5c000,0x40004000,0xbfb5c000,0x0,0x3fb50000,
0x40004000,0x3fb50000,0x0,0x3fb54000,0xbe490000,0xbfc60000,0xbfffc000,0xbfa2c000,0xbf15bec8,0xbf71bffb,0xbff5bffb,0x3fe23ec8,
0xbf71bf44,0x3ff53f44,0xbfe2bfed,0x3f153fed,0xbfa2bf8e,0x3e493fd5,0xbfc6bfd5,0xbfffbf8e,0xbffbc000,0xbf8ec000,0x3ec80000,0x3fd50000,
0xbfd5bfed,0x3ffb3f44,0x3f8e3f44,0x3ec83fed,0xbf8ebfb5,0xbec83fb5,0x3fd53fb5,0xbffbbfb5,0xbec8bf44,0xbfd5bfed,0x3ffb3fed,0x3f8ebf44,
0x3f150000,0x3fe20000,0x3ff54000,0x3f714000,0x3fc63f8e,0xbe493fd5,0x3fa23fd5,0xbfffbf8e,0x3fff3fed,0xbfc6bfed,0x3e493f44,0x3fa2bf44,
0x3fe23ffb,0x3ff53ec8,0xbf71bec8,0x3f153ffb,0x3fed4000,0x3f444000,0xbf440000,0xbfed0000,0x3f443fb5,0xbfedbfb5,0xbfedbfb5,0x3f44bfb5,
0xbf440000,0x3fed0000,0xbfedc000,0x3f444000,0xbfedbfb5,0xbf443fb5,0xbf44bfb5,0xbfedbfb5,0xbf710000,0xbff50000,0xbfe2c000,0xbf15c000,
0xbfffbfd5,0x3fa2bf8e,0xbe49bf8e,0x3fc63fd5,0xbfa2bfed,0xbe493fed,0x3fc63f44,0xbfffbf44,0x3f15bec8,0xbf71bffb,0x3ff53ffb,0x3fe2bec8,
0xbfd5c000,0xbec8c000,0x3f8e0000,0x3ffb0000,0x3ec8bf44,0x3f8e3fed,0x3ffb3fed,0xbfd53f44,0x3ffb3fb5,0xbfd5bfb5,0x3ec83fb5,0x3f8ebfb5,
0x3f8e3fed,0x3ffb3f44,0xbfd5bf44,0xbec83fed,0x3fa20000,0x3fff0000,0x3fc64000,0x3e494000,0x3fe23ffb,0xbff53ec8,0xbf713ec8,0xbf15bffb,
0xbf153f44,0x3fe2bf44,0xbff5bfed,0x3f713fed,0xbfffbfd5,0xbfc63f8e,0x3e49bf8e,0xbfa2bfd5,0x4000,0xbfb54000,0xc0000000,0xbfb50000,
0xc000,0x3fb50000,0x40000000,0xbfb54000,0x4000,0x3fb5c000,0xc0000000,0x3fb50000,0xc000,0xbfb50000,0x40000000,0x3fb5c000,
0xbfff0000,0xbfa20000,0x3e49c000,0x3fc6c000,0x3ff53ec8,0xbfe23ffb,0xbf153ffb,0xbf71bec8,0xbfe2bf44,0x3f153f44,0x3f71bfed,0xbff53fed,
0x3fc63f8e,0x3fffbfd5,0xbfa23fd5,0x3e493f8e,0x3ec8c000,0x3fd5c000,0x3ffb0000,0x3f8e0000,0xbf8e3fed,0xbec8bf44,0xbfd5bf44,0x3ffbbfed,
0x3fd5bfb5,0xbffb3fb5,0x3f8e3fb5,0x3ec8bfb5,0xbffb3f44,0xbf8e3fed,0xbec8bfed,0xbfd53f44,0x3ff50000,0x3f710000,0xbf154000,0xbfe24000,
0xbfa2bf8e,0x3fffbfd5,0x3fc6bfd5,0xbe493f8e,0x3e493fed,0x3fa2bfed,0xbfff3f44,0x3fc6bf44,0x3f71bffb,0xbf15bec8,0x3fe23ec8,0x3ff5bffb,
0xbf444000,0xbfed4000,0xbfed0000,0xbf440000,0x3fedbfb5,0xbf443fb5,0x3f443fb5,0xbfed3fb5,0xbfed0000,0x3f440000,0x3f44c000,0xbfed4000,
0x3f443fb5,0x3fedbfb5,0xbfed3fb5,0xbf443fb5,0xbfe20000,0xbf150000,0x3f71c000,0x3ff5c000,0x3e493fd5,0xbfc63f8e,0xbfff3f8e,0x3fa2bfd5,
0x3fc6bfed,0xbfff3fed,0x3fa23f44,0x3e49bf44,0xbff53ec8,0xbfe23ffb,0x3f15bffb,0xbf713ec8,0x3f8ec000,0x3ffbc000,0x3fd50000,0x3ec80000,
0xbffb3f44,0x3fd5bfed,0x3ec8bfed,0x3f8ebf44,0x3ec83fb5,0x3f8ebfb5,0xbffb3fb5,0x3fd5bfb5,0x3fd5bfed,0x3ec8bf44,0x3f8e3f44,0x3ffbbfed,
0x3fc60000,0x3e490000,0xbfa24000,0xbfff4000,0x3f71bffb,0x3f15bec8,0x3fe2bec8,0xbff53ffb,0xbff53f44,0x3f71bf44,0x3f15bfed,0xbfe23fed,
0xbe493fd5,0x3fa2bf8e,0xbfff3f8e,0xbfc63fd5,0xc0004000,0xbfb54000,0x0,0x3fb50000,0xc0004000,0x3fb50000,0x0,0x3fb5c000,
0xc0004000,0x3fb5c000,0x0,0xbfb50000,0xc0004000,0xbfb50000,0x0,0xbfb54000,0x3e490000,0x3fc60000,0x3fffc000,0x3fa2c000,
0x3f15bec8,0x3f71bffb,0x3ff5bffb,0xbfe23ec8,0x3f71bf44,0xbff53f44,0x3fe2bfed,0xbf153fed,0x3fa2bf8e,0xbe493fd5,0x3fc6bfd5,0x3fffbf8e,
0x3ffbc000,0x3f8ec000,0xbec80000,0xbfd50000,0x3fd5bfed,0xbffb3f44,0xbf8e3f44,0xbec83fed,0x3f8ebfb5,0x3ec83fb5,0xbfd53fb5,0x3ffbbfb5,
0x3ec8bf44,0x3fd5bfed,0xbffb3fed,0xbf8ebf44,0xbf150000,0xbfe20000,0xbff54000,0xbf714000,0xbfc63f8e,0x3e493fd5,0xbfa23fd5,0x3fffbf8e,
0xbfff3fed,0x3fc6bfed,0xbe493f44,0xbfa2bf44,0xbfe23ffb,0xbff53ec8,0x3f71bec8,0xbf153ffb,0xbfed4000,0xbf444000,0x3f440000,0x3fed0000,
0xbf443fb5,0x3fedbfb5,0x3fedbfb5,0xbf44bfb5,0x3f440000,0xbfed0000,0x3fedc000,0xbf444000,0x3fedbfb5,0x3f443fb5,0x3f44bfb5,0x3fedbfb5,
0x3f710000,0x3ff50000,0x3fe2c000,0x3f15c000,0x3fffbfd5,0xbfa2bf8e,0x3e49bf8e,0xbfc63fd5,0x3fa2bfed,0x3e493fed,0xbfc63f44,0x3fffbf44,
0xbf15bec8,0x3f71bffb,0xbff53ffb,0xbfe2bec8,0x3fd5c000,0x3ec8c000,0xbf8e0000,0xbffb0000,0xbec8bf44,0xbf8e3fed,0xbffb3fed,0x3fd53f44,
0xbffb3fb5,0x3fd5bfb5,0xbec83fb5,0xbf8ebfb5,0xbf8e3fed,0xbffb3f44,0x3fd5bf44,0x3ec83fed,0xbfa20000,0xbfff0000,0xbfc64000,0xbe494000,
0xbfe23ffb,0x3ff53ec8,0x3f713ec8,0x3f15bffb,0x3f153f44,0xbfe2bf44,0x3ff5bfed,0xbf713fed,0x3fffbfd5,0x3fc63f8e,0xbe49bf8e,0x3fa2bfd5,
0x4000,0x3fb54000,0x40000000,0x3fb50000,0xc000,0xbfb50000,0xc0000000,0x3fb54000,0x4000,0xbfb5c000,0x40000000,0xbfb50000,
0xc000,0x3fb50000,0xc0000000,0xbfb5c000,0x3fff0000,0x3fa20000,0xbe49c000,0xbfc6c000,0xbff53ec8,0x3fe23ffb,0x3f153ffb,0x3f71bec8,
0x3fe2bf44,0xbf153f44,0xbf71bfed,0x3ff53fed,0xbfc63f8e,0xbfffbfd5,0x3fa23fd5,0xbe493f8e,0xbec8c000,0xbfd5c000,0xbffb0000,0xbf8e0000,
0x3f8e3fed,0x3ec8bf44,0x3fd5bf44,0xbffbbfed,0xbfd5bfb5,0x3ffb3fb5,0xbf8e3fb5,0xbec8bfb5,0x3ffb3f44,0x3f8e3fed,0x3ec8bfed,0x3fd53f44,
0xbff50000,0xbf710000,0x3f154000,0x3fe24000,0x3fa2bf8e,0xbfffbfd5,0xbfc6bfd5,0x3e493f8e,0xbe493fed,0xbfa2bfed,0x3fff3f44,0xbfc6bf44,
0xbf71bffb,0x3f15bec8,0xbfe23ec8,0xbff5bffb,0x3f444000,0x3fed4000,0x3fed0000,0x3f440000,0xbfedbfb5,0x3f443fb5,0xbf443fb5,0x3fed3fb5,
0x3fed0000,0xbf440000,0xbf44c000,0x3fed4000,0xbf443fb5,0xbfedbfb5,0x3fed3fb5,0x3f443fb5,0x3fe20000,0x3f150000,0xbf71c000,0xbff5c000,
0xbe493fd5,0x3fc63f8e,0x3fff3f8e,0xbfa2bfd5,0xbfc6bfed,0x3fff3fed,0xbfa23f44,0xbe49bf44,0x3ff53ec8,0x3fe23ffb,0xbf15bffb,0x3f713ec8,
0xbf8ec000,0xbffbc000,0xbfd50000,0xbec80000,0x3ffb3f44,0xbfd5bfed,0xbec8bfed,0xbf8ebf44,0xbec83fb5,0xbf8ebfb5,0x3ffb3fb5,0xbfd5bfb5,
0xbfd5bfed,0xbec8bf44,0xbf8e3f44,0xbffbbfed,0xbfc60000,0xbe490000,0x3fa24000,0x3fff4000,0xbf71bffb,0xbf15bec8,0xbfe2bec8,0x3ff53ffb,
0x3ff53f44,0xbf71bf44,0xbf15bfed,0x3fe23fed,0x3e493fd5,0xbfa2bf8e,0x3fff3f8e,0x3fc63fd5,0x40004000,0x3fb54000,0x0,0xbfb50000,
0x40004000,0xbfb50000,0x0,0xbfb5c000,0x40004000,0xbfb5c000,0x0,0x3fb50000,0x40004000,0x3fb50000,0x0,0x3fb54000,
0xbfc6bfb5,0xbfffbfb5,0xbfa2bfb5,0x3e49bfb5,0xbfe2bfd5,0x3f15bf8e,0xbf71bf8e,0x3ff53fd5,0xbff5bfed,0x3fe23fed,0xbf15bf44,0xbf713f44,
0xbfffbffb,0xbfa23ec8,0xbe49bec8,0xbfc6bffb,0x3ec80000,0x3fd50000,0x3ffb4000,0x3f8e4000,0x3f8e3f44,0x3ec83fed,0x3fd53fed,0xbffbbf44,
0x3fd53fb5,0xbffbbfb5,0x3f8e3fb5,0x3ec8bfb5,0x3ffb3fed,0x3f8ebf44,0x3ec83f44,0x3fd53fed,0x3f713fb5,0xbf153fb5,0xbfe2bfb5,0xbff5bfb5,
0xbe493ec8,0xbfa2bffb,0xbfffbffb,0x3fc6bec8,0xbfa2bf44,0x3fff3f44,0xbfc6bfed,0x3e493fed,0xbff5bfd5,0xbf713f8e,0xbf15bf8e,0xbfe2bfd5,
0xbfedc000,0xbf44c000,0x3f440000,0x3fed0000,0xbf44bfb5,0x3fed3fb5,0x3fed3fb5,0xbf443fb5,0x3f440000,0xbfed0000,0x3fed4000,0xbf44c000,
0x3fed3fb5,0x3f44bfb5,0x3f443fb5,0x3fed3fb5,0x3ff53fb5,0x3fe23fb5,0x3f153fb5,0xbf713fb5,0x3fc63ffb,0xbfffbec8,0xbfa2bec8,0xbe49bffb,
0xbe493f44,0x3fc6bf44,0xbfffbfed,0x3fa23fed,0xbfe2bf8e,0xbf153fd5,0xbf71bfd5,0xbff5bf8e,0xbf8e0000,0xbffb0000,0xbfd5c000,0xbec8c000,
0xbffbbfed,0x3fd5bf44,0x3ec8bf44,0x3f8e3fed,0xbec8bfb5,0xbf8e3fb5,0x3ffb3fb5,0xbfd5bfb5,0x3fd53f44,0x3ec8bfed,0x3f8e3fed,0x3ffb3f44,
0xbe49bfb5,0x3fa2bfb5,0x3fff3fb5,0x3fc63fb5,0x3ff53f8e,0xbf713fd5,0x3f153fd5,0xbfe2bf8e,0x3f713fed,0x3f15bfed,0xbfe2bf44,0x3ff53f44,
0xbfc6bec8,0xbe493ffb,0xbfa2bffb,0xbfffbec8,0x4000,0xbfb54000,0xc0000000,0xbfb50000,0xc000,0x3fb50000,0x40000000,0xbfb54000,
0x4000,0x3fb5c000,0xc0000000,0x3fb50000,0xc000,0xbfb50000,0x40000000,0x3fb5c000,0xbfa2bfb5,0x3e49bfb5,0x3fc6bfb5,0x3fffbfb5,
0x3f713fd5,0xbff53f8e,0xbfe23f8e,0x3f15bfd5,0xbf15bfed,0xbf713fed,0x3ff5bf44,0xbfe23f44,0x3e493ffb,0x3fc6bec8,0xbfff3ec8,0xbfa23ffb,
0x3ffb0000,0x3f8e0000,0xbec84000,0xbfd54000,0xbfd5bf44,0x3ffbbfed,0x3f8ebfed,0x3ec83f44,0x3f8e3fb5,0x3ec8bfb5,0xbfd53fb5,0x3ffbbfb5,
0xbec8bfed,0xbfd53f44,0x3ffbbf44,0x3f8ebfed,0xbfe23fb5,0xbff53fb5,0xbf71bfb5,0x3f15bfb5,0x3fffbec8,0xbfc63ffb,0xbe493ffb,0xbfa23ec8,
0xbfc6bf44,0x3e493f44,0x3fa2bfed,0xbfff3fed,0x3f153fd5,0x3fe2bf8e,0xbff53f8e,0xbf713fd5,0x3f44c000,0x3fedc000,0x3fed0000,0x3f440000,
0xbfed3fb5,0x3f44bfb5,0xbf44bfb5,0x3fedbfb5,0x3fed0000,0xbf440000,0xbf444000,0x3fedc000,0xbf44bfb5,0xbfed3fb5,0x3fedbfb5,0x3f44bfb5,
0x3f153fb5,0xbf713fb5,0xbff53fb5,0xbfe23fb5,0x3fa2bffb,0x3e493ec8,0x3fc63ec8,0xbfff3ffb,0xbfff3f44,0x3fa2bf44,0x3e49bfed,0xbfc63fed,
0x3f713f8e,0x3ff5bfd5,0xbfe23fd5,0xbf153f8e,0xbfd50000,0xbec80000,0x3f8ec000,0x3ffbc000,0xbec83fed,0xbf8e3f44,0xbffb3f44,0x3fd5bfed,
0x3ffbbfb5,0xbfd53fb5,0x3ec83fb5,0x3f8ebfb5,0xbf8ebf44,0xbffb3fed,0x3fd5bfed,0x3ec8bf44,0x3fffbfb5,0x3fc6bfb5,0x3e493fb5,0xbfa23fb5,
0xbf15bf8e,0x3fe2bfd5,0x3ff5bfd5,0xbf713f8e,0xbfe23fed,0x3ff5bfed,0xbf71bf44,0xbf153f44,0x3fa23ec8,0x3fffbffb,0xbfc63ffb,0xbe493ec8,
0xc0004000,0xbfb54000,0x0,0x3fb50000,0xc0004000,0x3fb50000,0x0,0x3fb5c000,0xc0004000,0x3fb5c000,0x0,0xbfb50000,
0xc0004000,0xbfb50000,0x0,0xbfb54000,0x3fc6bfb5,0x3fffbfb5,0x3fa2bfb5,0xbe49bfb5,0x3fe2bfd5,0xbf15bf8e,0x3f71bf8e,0xbff53fd5,
0x3ff5bfed,0xbfe23fed,0x3f15bf44,0x3f713f44,0x3fffbffb,0x3fa23ec8,0x3e49bec8,0x3fc6bffb,0xbec80000,0xbfd50000,0xbffb4000,0xbf8e4000,
0xbf8e3f44,0xbec83fed,0xbfd53fed,0x3ffbbf44,0xbfd53fb5,0x3ffbbfb5,0xbf8e3fb5,0xbec8bfb5,0xbffb3fed,0xbf8ebf44,0xbec83f44,0xbfd53fed,
0xbf713fb5,0x3f153fb5,0x3fe2bfb5,0x3ff5bfb5,0x3e493ec8,0x3fa2bffb,0x3fffbffb,0xbfc6bec8,0x3fa2bf44,0xbfff3f44,0x3fc6bfed,0xbe493fed,
0x3ff5bfd5,0x3f713f8e,0x3f15bf8e,0x3fe2bfd5,0x3fedc000,0x3f44c000,0xbf440000,0xbfed0000,0x3f44bfb5,0xbfed3fb5,0xbfed3fb5,0x3f443fb5,
0xbf440000,0x3fed0000,0xbfed4000,0x3f44c000,0xbfed3fb5,0xbf44bfb5,0xbf443fb5,0xbfed3fb5,0xbff53fb5,0xbfe23fb5,0xbf153fb5,0x3f713fb5,
0xbfc63ffb,0x3fffbec8,0x3fa2bec8,0x3e49bffb,0x3e493f44,0xbfc6bf44,0x3fffbfed,0xbfa23fed,0x3fe2bf8e,0x3f153fd5,0x3f71bfd5,0x3ff5bf8e,
0x3f8e0000,0x3ffb0000,0x3fd5c000,0x3ec8c000,0x3ffbbfed,0xbfd5bf44,0xbec8bf44,0xbf8e3fed,0x3ec8bfb5,0x3f8e3fb5,0xbffb3fb5,0x3fd5bfb5,
0xbfd53f44,0xbec8bfed,0xbf8e3fed,0xbffb3f44,0x3e49bfb5,0xbfa2bfb5,0xbfff3fb5,0xbfc63fb5,0xbff53f8e,0x3f713fd5,0xbf153fd5,0x3fe2bf8e,
0xbf713fed,0xbf15bfed,0x3fe2bf44,0xbff53f44,0x3fc6bec8,0x3e493ffb,0x3fa2bffb,0x3fffbec8,0x4000,0x3fb54000,0x40000000,0x3fb50000,
0xc000,0xbfb50000,0xc0000000,0x3fb54000,0x4000,0xbfb5c000,0x40000000,0xbfb50000,0xc000,0x3fb50000,0xc0000000,0xbfb5c000,
0x3fa2bfb5,0xbe49bfb5,0xbfc6bfb5,0xbfffbfb5,0xbf713fd5,0x3ff53f8e,0x3fe23f8e,0xbf15bfd5,0x3f15bfed,0x3f713fed,0xbff5bf44,0x3fe23f44,
0xbe493ffb,0xbfc6bec8,0x3fff3ec8,0x3fa23ffb,0xbffb0000,0xbf8e0000,0x3ec84000,0x3fd54000,0x3fd5bf44,0xbffbbfed,0xbf8ebfed,0xbec83f44,
0xbf8e3fb5,0xbec8bfb5,0x3fd53fb5,0xbffbbfb5,0x3ec8bfed,0x3fd53f44,0xbffbbf44,0xbf8ebfed,0x3fe23fb5,0x3ff53fb5,0x3f71bfb5,0xbf15bfb5,
0xbfffbec8,0x3fc63ffb,0x3e493ffb,0x3fa23ec8,0x3fc6bf44,0xbe493f44,0xbfa2bfed,0x3fff3fed,0xbf153fd5,0xbfe2bf8e,0x3ff53f8e,0x3f713fd5,
0xbf44c000,0xbfedc000,0xbfed0000,0xbf440000,0x3fed3fb5,0xbf44bfb5,0x3f44bfb5,0xbfedbfb5,0xbfed0000,0x3f440000,0x3f444000,0xbfedc000,
0x3f44bfb5,0x3fed3fb5,0xbfedbfb5,0xbf44bfb5,0xbf153fb5,0x3f713fb5,0x3ff53fb5,0x3fe23fb5,0xbfa2bffb,0xbe493ec8,0xbfc63ec8,0x3fff3ffb,
0x3fff3f44,0xbfa2bf44,0xbe49bfed,0x3fc63fed,0xbf713f8e,0xbff5bfd5,0x3fe23fd5,0x3f153f8e,0x3fd50000,0x3ec80000,0xbf8ec000,0xbffbc000,
0x3ec83fed,0x3f8e3f44,0x3ffb3f44,0xbfd5bfed,0xbffbbfb5,0x3fd53fb5,0xbec83fb5,0xbf8ebfb5,0x3f8ebf44,0x3ffb3fed,0xbfd5bfed,0xbec8bf44,
0xbfffbfb5,0xbfc6bfb5,0xbe493fb5,0x3fa23fb5,0x3f15bf8e,0xbfe2bfd5,0xbff5bfd5,0x3f713f8e,0x3fe23fed,0xbff5bfed,0x3f71bf44,0x3f153f44,
0xbfa23ec8,0xbfffbffb,0x3fc63ffb,0x3e493ec8,0x80003f80,0x3f800000,0x80003f80,0x3f800000,0x80003f80,0x3f800000,0x80003f80,0x3f800000,
0x80003f80,0x3f800000,0x80003f80,0x3f800000,0x80003f80,0x3f800000,0x80003f80,0x3f800000,0x80003f80,0x3f800000,0x8000bf80,0xbf800000,
0x3f353f35,0x3f35bf35,0xbf35bf35,0xbf353f35,0x3f800000,0xbf80,0xbf800000,0x3f80,0x3f35bf35,0xbf35bf35,0xbf353f35,0x3f353f35,
0x80003f80,0x3f800000,0x80003f80,0x3f800000,0x3f800000,0xbf80,0x3f800000,0xbf80,0x8000bf80,0xbf800000,0x8000bf80,0xbf800000,
0xbf800000,0x3f80,0xbf800000,0x3f80,0x80003f80,0x3f800000,0x8000bf80,0xbf800000,0x3f35bf35,0xbf35bf35,0xbf353f35,0x3f353f35,
0xbf800000,0x3f80,0x3f800000,0xbf80,0x3f353f35,0x3f35bf35,0xbf35bf35,0xbf353f35,0x80003f80,0x3f800000,0x80003f80,0x3f800000,
0x8000bf80,0xbf800000,0x8000bf80,0xbf800000,0x80003f80,0x3f800000,0x80003f80,0x3f800000,0x8000bf80,0xbf800000,0x8000bf80,0xbf800000,
0x80003f80,0x3f800000,0x8000bf80,0xbf800000,0xbf35bf35,0xbf353f35,0x3f353f35,0x3f35bf35,0x3f800000,0xbf80,0xbf800000,0x3f80,
0xbf353f35,0x3f353f35,0x3f35bf35,0xbf35bf35,0x80003f80,0x3f800000,0x80003f80,0x3f800000,0xbf800000,0x3f80,0xbf800000,0x3f80,
0x8000bf80,0xbf800000,0x8000bf80,0xbf800000,0x3f800000,0xbf80,0x3f800000,0xbf80,0x80003f80,0x3f800000,0x8000bf80,0xbf800000,
0xbf353f35,0x3f353f35,0x3f35bf35,0xbf35bf35,0xbf800000,0x3f80,0x3f800000,0xbf80,0xbf35bf35,0xbf353f35,0x3f353f35,0x3f35bf35,
0x3f803f80,0x80008000,0x80008000,0xbf80bf80,0x3f803f80,0x80008000,0x80008000,0xbf80bf80,0x3f803f80,0x80008000,0x80008000,0xbf80bf80,
0x3f803f80,0x80008000,0x80008000,0xbf80bf80,0x3f353f80,0x3f358000,0x3f358000,0xbf35bf80,0xbf350000,0x3f353f80,0x3f353f80,0x3f358000,
0xbf35bf80,0xbf358000,0xbf358000,0x3f353f80,0x3f350000,0xbf35bf80,0xbf35bf80,0xbf358000,0x3f80,0x3f808000,0x3f808000,0x8000bf80,
0xbf80,0xbf808000,0xbf808000,0x80003f80,0x3f80,0x3f808000,0x3f808000,0x8000bf80,0xbf80,0xbf808000,0xbf808000,0x80003f80,
0xbf353f80,0x3f358000,0x3f358000,0x3f35bf80,0x3f350000,0x3f35bf80,0x3f35bf80,0xbf358000,0x3f35bf80,0xbf358000,0xbf358000,0xbf353f80,
0xbf350000,0xbf353f80,0xbf353f80,0x3f358000,0xbf803f80,0x80008000,0x80008000,0x3f80bf80,0xbf803f80,0x80008000,0x80008000,0x3f80bf80,
0xbf803f80,0x80008000,0x80008000,0x3f80bf80,0xbf803f80,0x80008000,0x80008000,0x3f80bf80,0xbf353f80,0xbf358000,0xbf358000,0x3f35bf80,
0x3f350000,0xbf353f80,0xbf353f80,0xbf358000,0x3f35bf80,0x3f358000,0x3f358000,0xbf353f80,0xbf350000,0x3f35bf80,0x3f35bf80,0x3f358000,
0x3f80,0xbf808000,0xbf808000,0x8000bf80,0xbf80,0x3f808000,0x3f808000,0x80003f80,0x3f80,0xbf808000,0xbf808000,0x8000bf80,
0xbf80,0x3f808000,0x3f808000,0x80003f80,0x3f353f80,0xbf358000,0xbf358000,0xbf35bf80,0xbf350000,0xbf35bf80,0xbf35bf80,0x3f358000,
0xbf35bf80,0x3f358000,0x3f358000,0x3f353f80,0x3f350000,0x3f353f80,0x3f353f80,0xbf358000,0x3f800000,0x0,0x3f800000,0x0,
0x3f800000,0x0,0x3f800000,0x0,0x3f800000,0x0,0x3f800000,0x0,0x3f800000,0x0,0x3f800000,0x0,
0x3f800000,0x0,0x3f7fb10f,0xbd48fb30,0x3f7ec46d,0xbdc8bd36,0x3f7d3aac,0xbe164083,0x3f7b14be,0xbe47c5c2,0x3f7853f8,0xbe78cfcc,
0x3f74fa0b,0xbe94a031,0x3f710908,0xbeac7cd4,0x3f800000,0x0,0x3f7ec46d,0xbdc8bd36,0x3f7b14be,0xbe47c5c2,0x3f74fa0b,0xbe94a031,
0x3f6c835e,0xbec3ef15,0x3f61c598,0xbef15aea,0x3f54db31,0xbf0e39da,0x3f45e403,0xbf226799,0x3f800000,0x0,0x3f7d3aac,0xbe164083,
0x3f74fa0b,0xbe94a031,0x3f676bd8,0xbedae880,0x3f54db31,0xbf0e39da,0x3f3daef9,0xbf2beb4a,0x3f226799,0xbf45e403,0x3f039c3d,0xbf5b941a,
0x3f800000,0x0,0x3f7b14be,0xbe47c5c2,0x3f6c835e,0xbec3ef15,0x3f54db31,0xbf0e39da,0x3f3504f3,0xbf3504f3,0x3f0e39da,0xbf54db31,
0x3ec3ef15,0xbf6c835e,0x3e47c5c2,0xbf7b14be,0x3f800000,0x0,0x3f7853f8,0xbe78cfcc,0x3f61c598,0xbef15aea,0x3f3daef9,0xbf2beb4a,
0x3f0e39da,0xbf54db31,0x3eac7cd4,0xbf710908,0x3dc8bd36,0xbf7ec46d,0xbe164083,0xbf7d3aac,0x3f800000,0x0,0x3f74fa0b,0xbe94a031,
0x3f54db31,0xbf0e39da,0x3f226799,0xbf45e403,0x3ec3ef15,0xbf6c835e,0x3dc8bd36,0xbf7ec46d,0xbe47c5c2,0xbf7b14be,0xbef15aea,0xbf61c598,
0x3f800000,0x0,0x3f710908,0xbeac7cd4,0x3f45e403,0xbf226799,0x3f039c3d,0xbf5b941a,0x3e47c5c2,0xbf7b14be,0xbe164083,0xbf7d3aac,
0xbef15aea,0xbf61c598,0xbf3daef9,0xbf2beb4a,0x3f800000,0x0,0x3f800000,0x0,0x3f800000,0x0,0x3f800000,0x0,
0x3f800000,0x0,0x3f800000,0x0,0x3f800000,0x0,0x3f800000,0x0,0x3f6c835e,0xbec3ef15,0x3f676bd8,0xbedae880,
0x3f61c598,0xbef15aea,0x3f5b941a,0xbf039c3d,0x3f54db31,0xbf0e39da,0x3f4d9f02,0xbf187fc0,0x3f45e403,0xbf226799,0x3f3daef9,0xbf2beb4a,
0x3f3504f3,0xbf3504f3,0x3f226799,0xbf45e403,0x3f0e39da,0xbf54db31,0x3ef15aea,0xbf61c598,0x3ec3ef15,0xbf6c835e,0x3e94a031,0xbf74fa0b,
0x3e47c5c2,0xbf7b14be,0x3dc8bd36,0xbf7ec46d,0x3ec3ef15,0xbf6c835e,0x3e78cfcc,0xbf7853f8,0x3dc8bd36,0xbf7ec46d,0xbd48fb30,0xbf7fb10f,
0xbe47c5c2,0xbf7b14be,0xbeac7cd4,0xbf710908,0xbef15aea,0xbf61c598,0xbf187fc0,0xbf4d9f02,0x0,0xbf800000,0xbe47c5c2,0xbf7b14be,
0xbec3ef15,0xbf6c835e,0xbf0e39da,0xbf54db31,0xbf3504f3,0xbf3504f3,0xbf54db31,0xbf0e39da,0xbf6c835e,0xbec3ef15,0xbf7b14be,0xbe47c5c2,
0xbec3ef15,0xbf6c835e,0xbf187fc0,0xbf4d9f02,0xbf45e403,0xbf226799,0xbf676bd8,0xbedae880,0xbf7b14be,0xbe47c5c2,0xbf7fb10f,0x3d48fb30,
0xbf74fa0b,0x3e94a031,0xbf5b941a,0x3f039c3d,0xbf3504f3,0xbf3504f3,0xbf61c598,0xbef15aea,0xbf7b14be,0xbe47c5c2,0xbf7ec46d,0x3dc8bd36,
0xbf6c835e,0x3ec3ef15,0xbf45e403,0x3f226799,0xbf0e39da,0x3f54db31,0xbe94a031,0x3f74fa0b,0xbf6c835e,0xbec3ef15,0xbf7fb10f,0xbd48fb30,
0xbf74fa0b,0x3e94a031,0xbf4d9f02,0x3f187fc0,0xbf0e39da,0x3f54db31,0xbe78cfcc,0x3f7853f8,0x3dc8bd36,0x3f7ec46d,0x3edae880,0x3f676bd8,
0x80003f80,0x3f800000,0x3f800000,0xbf80,0x3ec43f6d,0x3f6dbec4,0x3f6dbec4,0xbec4bf6d,0x3f353f35,0x3f35bf35,0x3f35bf35,0xbf35bf35,
0x3f6d3ec4,0x3ec4bf6d,0x3ec4bf6d,0xbf6dbec4,0x80003f80,0x3f800000,0xbf800000,0x3f80,0x3f6d3ec4,0x3ec4bf6d,0xbec43f6d,0x3f6d3ec4,
0x3f35bf35,0xbf35bf35,0x3f353f35,0x3f35bf35,0xbec4bf6d,0xbf6d3ec4,0x3f6dbec4,0xbec4bf6d,0x80003f80,0x3f800000,0x3f800000,0xbf80,
0x3f6dbec4,0xbec4bf6d,0xbec4bf6d,0xbf6d3ec4,0xbf35bf35,0xbf353f35,0xbf353f35,0x3f353f35,0xbec43f6d,0x3f6d3ec4,0x3f6d3ec4,0x3ec4bf6d,
0x80003f80,0x3f800000,0xbf800000,0x3f80,0x3ec4bf6d,0xbf6dbec4,0x3f6d3ec4,0x3ec4bf6d,0xbf353f35,0x3f353f35,0xbf35bf35,0xbf353f35,
0x3f6dbec4,0xbec4bf6d,0x3ec43f6d,0x3f6dbec4,0x80003f80,0x3f800000,0x3f800000,0xbf80,0xbec4bf6d,0xbf6d3ec4,0xbf6d3ec4,0x3ec43f6d,
0x3f353f35,0x3f35bf35,0x3f35bf35,0xbf35bf35,0xbf6dbec4,0xbec43f6d,0xbec43f6d,0x3f6d3ec4,0x80003f80,0x3f800000,0xbf800000,0x3f80,
0xbf6dbec4,0xbec43f6d,0x3ec4bf6d,0xbf6dbec4,0x3f35bf35,0xbf35bf35,0x3f353f35,0x3f35bf35,0x3ec43f6d,0x3f6dbec4,0xbf6d3ec4,0x3ec43f6d,
0x80003f80,0x3f800000,0x3f800000,0xbf80,0xbf6d3ec4,0x3ec43f6d,0x3ec43f6d,0x3f6dbec4,0xbf35bf35,0xbf353f35,0xbf353f35,0x3f353f35,
0x3ec4bf6d,0xbf6dbec4,0xbf6dbec4,0xbec43f6d,0x80003f80,0x3f800000,0xbf800000,0x3f80,0xbec43f6d,0x3f6d3ec4,0xbf6dbec4,0xbec43f6d,
0xbf353f35,0x3f353f35,0xbf35bf35,0xbf353f35,0xbf6d3ec4,0x3ec43f6d,0xbec4bf6d,0xbf6d3ec4,0x3f803f80,0x80008000,0x80008000,0xbf80bf80,
0x3f803f80,0x80008000,0x80008000,0xbf80bf80,0x3f803f80,0x80008000,0x80008000,0xbf80bf80,0x3f803f80,0x80008000,0x80008000,0xbf80bf80,
0x3ec43f6d,0x3f6d3ec4,0x3f6d3ec4,0xbec4bf6d,0xbf6dbec4,0x3ec43f6d,0x3ec43f6d,0x3f6d3ec4,0xbec4bf6d,0xbf6dbec4,0xbf6dbec4,0x3ec43f6d,
0x3f6d3ec4,0xbec4bf6d,0xbec4bf6d,0xbf6dbec4,0xbf353f35,0x3f353f35,0x3f353f35,0x3f35bf35,0x3f35bf35,0xbf35bf35,0xbf35bf35,0xbf353f35,
0xbf353f35,0x3f353f35,0x3f353f35,0x3f35bf35,0x3f35bf35,0xbf35bf35,0xbf35bf35,0xbf353f35,0xbf6d3ec4,0xbec43f6d,0xbec43f6d,0x3f6dbec4,
0xbec43f6d,0x3f6dbec4,0x3f6dbec4,0x3ec4bf6d,0x3f6dbec4,0x3ec4bf6d,0x3ec4bf6d,0xbf6d3ec4,0x3ec4bf6d,0xbf6d3ec4,0xbf6d3ec4,0xbec43f6d,
0x0,0xbf803f80,0xbf803f80,0x80008000,0x0,0xbf803f80,0xbf803f80,0x80008000,0x0,0xbf803f80,0xbf803f80,0x80008000,
0x0,0xbf803f80,0xbf803f80,0x80008000,0x3f6dbec4,0xbec43f6d,0xbec43f6d,0xbf6d3ec4,0x3ec4bf6d,0x3f6dbec4,0x3f6dbec4,0xbec43f6d,
0xbf6d3ec4,0x3ec4bf6d,0x3ec4bf6d,0x3f6dbec4,0xbec43f6d,0xbf6d3ec4,0xbf6d3ec4,0x3ec4bf6d,0x3f35bf35,0x3f353f35,0x3f353f35,0xbf353f35,
0xbf353f35,0xbf35bf35,0xbf35bf35,0x3f35bf35,0x3f35bf35,0x3f353f35,0x3f353f35,0xbf353f35,0xbf353f35,0xbf35bf35,0xbf35bf35,0x3f35bf35,
0xbec4bf6d,0x3f6d3ec4,0x3f6d3ec4,0x3ec43f6d,0x3f6d3ec4,0x3ec43f6d,0x3ec43f6d,0xbf6dbec4,0x3ec43f6d,0xbf6dbec4,0xbf6dbec4,0xbec4bf6d,
0xbf6dbec4,0xbec4bf6d,0xbec4bf6d,0x3f6d3ec4,0x3f800000,0x0,0x3f7fec43,0xbcc90ab0,0x3f7fb10f,0xbd48fb30,0x3f7f4e6d,0xbd96a905,
0x3f7ec46d,0xbdc8bd36,0x3f7e1324,0xbdfab273,0x3f7d3aac,0xbe164083,0x3f7c3b28,0xbe2f10a2,0x3f800000,0x0,0x3f7f4e6d,0xbd96a905,
0x3f7d3aac,0xbe164083,0x3f79c79d,0xbe605c13,0x3f74fa0b,0xbe94a031,0x3f6ed89e,0xbeb8442a,0x3f676bd8,0xbedae880,0x3f5ebe05,0xbefc5d27,
0x3f800000,0x0,0x3f7e1324,0xbdfab273,0x3f7853f8,0xbe78cfcc,0x3f6ed89e,0xbeb8442a,0x3f61c598,0xbef15aea,0x3f514d3d,0xbf13682a,
0x3f3daef9,0xbf2beb4a,0x3f273656,0xbf41d870,0x3f800000,0x0,0x3f7c3b28,0xbe2f10a2,0x3f710908,0xbeac7cd4,0x3f5ebe05,0xbefc5d27,
0x3f45e403,0xbf226799,0x3f273656,0xbf41d870,0x3f039c3d,0xbf5b941a,0x3eb8442a,0xbf6ed89e,0x3f800000,0x0,0x3f79c79d,0xbe605c13,
0x3f676bd8,0xbedae880,0x3f49d112,0xbf1d7fd1,0x3f226799,0xbf45e403,0x3ee63375,0xbf64aa59,0x3e78cfcc,0xbf7853f8,0x3cc90ab0,0xbf7fec43,
0x3f800000,0x0,0x3f76ba07,0xbe888e93,0x3f5b941a,0xbf039c3d,0x3f3085bb,0xbf396842,0x3ef15aea,0xbf61c598,0x3e605c13,0xbf79c79d,
0xbd48fb30,0xbf7fb10f,0xbea09ae5,0xbf731447,0x3f800000,0x0,0x3f731447,0xbea09ae5,0x3f4d9f02,0xbf187fc0,0x3f13682a,0xbf514d3d,
0x3e94a031,0xbf74fa0b,0xbcc90ab0,0xbf7fec43,0xbeac7cd4,0xbf710908,0xbf1d7fd1,0xbf49d112,0x3f800000,0x0,0x3f6ed89e,0xbeb8442a,
0x3f3daef9,0xbf2beb4a,0x3ee63375,0xbf64aa59,0x3dc8bd36,0xbf7ec46d,0xbe888e93,0xbf76ba07,0xbf187fc0,0xbf4d9f02,0xbf584853,0xbf08f59b,
0x3f7b14be,0xbe47c5c2,0x3f79c79d,0xbe605c13,0x3f7853f8,0xbe78cfcc,0x3f76ba07,0xbe888e93,0x3f74fa0b,0xbe94a031,0x3f731447,0xbea09ae5,
0x3f710908,0xbeac7cd4,0x3f6ed89e,0xbeb8442a,0x3f54db31,0xbf0e39da,0x3f49d112,0xbf1d7fd1,0x3f3daef9,0xbf2beb4a,0x3f3085bb,0xbf396842,
0x3f226799,0xbf45e403,0x3f13682a,0xbf514d3d,0x3f039c3d,0xbf5b941a,0x3ee63375,0xbf64aa59,0x3f0e39da,0xbf54db31,0x3ee63375,0xbf64aa59,
0x3eac7cd4,0xbf710908,0x3e605c13,0xbf79c79d,0x3dc8bd36,0xbf7ec46d,0xbcc90ab0,0xbf7fec43,0xbe164083,0xbf7d3aac,0xbe888e93,0xbf76ba07,
0x3e47c5c2,0xbf7b14be,0x3cc90ab0,0xbf7fec43,0xbe164083,0xbf7d3aac,0xbea09ae5,0xbf731447,0xbef15aea,0xbf61c598,0xbf1d7fd1,0xbf49d112,
0xbf3daef9,0xbf2beb4a,0xbf584853,0xbf08f59b,0xbe47c5c2,0xbf7b14be,0xbecf7bca,0xbf6a09a7,0xbf187fc0,0xbf4d9f02,0xbf41d870,0xbf273656,
0xbf61c598,0xbef15aea,0xbf76ba07,0xbe888e93,0xbf7fb10f,0xbd48fb30,0xbf7c3b28,0x3e2f10a2,0xbf0e39da,0xbf54db31,0xbf41d870,0xbf273656,
0xbf676bd8,0xbedae880,0xbf7c3b28,0xbe2f10a2,0xbf7ec46d,0x3dc8bd36,0xbf6ed89e,0x3eb8442a,0xbf4d9f02,0x3f187fc0,0xbf1d7fd1,0x3f49d112,
0xbf54db31,0xbf0e39da,0xbf76ba07,0xbe888e93,0xbf7fb10f,0x3d48fb30,0xbf6ed89e,0x3eb8442a,0xbf45e403,0x3f226799,0xbf08f59b,0x3f584853,
0xbe78cfcc,0x3f7853f8,0x3d96a905,0x3f7f4e6d,0xbf7b14be,0xbe47c5c2,0xbf7c3b28,0x3e2f10a2,0xbf5b941a,0x3f039c3d,0xbf1d7fd1,0x3f49d112,
0xbe94a031,0x3f74fa0b,0x3d96a905,0x3f7f4e6d,0x3edae880,0x3f676bd8,0x3f396842,0x3f3085bb,0x80003f80,0x80003f80,0x80003f80,0x80003f80,
0x80003f80,0x80003f80,0x80003f80,0x80003f80,0x80003f80,0x80003f80,0x80003f80,0x80003f80,0x80003f80,0x80003f80,0x80003f80,0x80003f80,
0x3f800000,0x3f800000,0x3f800000,0x3f800000,0x3f800000,0x3f800000,0x3f800000,0x3f800000,0x3f800000,0x3f800000,0x3f800000,0x3f800000,
0x3f800000,0x3f800000,0x3f800000,0x3f800000,0x80003f80,0x3f353f35,0x80003f80,0x3f353f35,0x3f800000,0x3f35bf35,0x3f800000,0x3f35bf35,
0x8000bf80,0xbf35bf35,0x8000bf80,0xbf35bf35,0xbf800000,0xbf353f35,0xbf800000,0xbf353f35,0x3f800000,0x3f35bf35,0x3f800000,0x3f35bf35,
0xbf80,0xbf35bf35,0xbf80,0xbf35bf35,0xbf800000,0xbf353f35,0xbf800000,0xbf353f35,0x3f80,0x3f353f35,0x3f80,0x3f353f35,
0x80003f80,0x3f800000,0x80003f80,0x3f800000,0x8000bf80,0xbf800000,0x8000bf80,0xbf800000,0x80003f80,0x3f800000,0x80003f80,0x3f800000,
0x8000bf80,0xbf800000,0x8000bf80,0xbf800000,0x3f800000,0xbf80,0x3f800000,0xbf80,0xbf800000,0x3f80,0xbf800000,0x3f80,
0x3f800000,0xbf80,0x3f800000,0xbf80,0xbf800000,0x3f80,0xbf800000,0x3f80,0x80003f80,0x3f35bf35,0x80003f80,0x3f35bf35,
0xbf800000,0x3f353f35,0xbf800000,0x3f353f35,0x8000bf80,0xbf353f35,0x8000bf80,0xbf353f35,0x3f800000,0xbf35bf35,0x3f800000,0xbf35bf35,
0x3f800000,0xbf35bf35,0x3f800000,0xbf35bf35,0x3f80,0x3f35bf35,0x3f80,0x3f35bf35,0xbf800000,0x3f353f35,0xbf800000,0x3f353f35,
0xbf80,0xbf353f35,0xbf80,0xbf353f35,0x80003f80,0x3ec43f6d,0x8000bf80,0xbec4bf6d,0x3f353f35,0x3f6d3ec4,0xbf35bf35,0xbf6dbec4,
0x3f800000,0x3f6dbec4,0xbf800000,0xbf6d3ec4,0x3f35bf35,0x3ec4bf6d,0xbf353f35,0xbec43f6d,0x3f800000,0x3f6dbec4,0xbf800000,0xbf6d3ec4,
0x3f35bf35,0x3ec4bf6d,0xbf353f35,0xbec43f6d,0xbf80,0xbec4bf6d,0x3f80,0x3ec43f6d,0xbf35bf35,0xbf6dbec4,0x3f353f35,0x3f6d3ec4,
0x80003f80,0x3f6d3ec4,0x8000bf80,0xbf6dbec4,0x3f35bf35,0xbec4bf6d,0xbf353f35,0x3ec43f6d,0xbf800000,0xbec43f6d,0x3f800000,0x3ec4bf6d,
0x3f353f35,0x3f6dbec4,0xbf35bf35,0xbf6d3ec4,0x3f800000,0x3ec4bf6d,0xbf800000,0xbec43f6d,0xbf35bf35,0xbf6d3ec4,0x3f353f35,0x3f6dbec4,
0x3f80,0x3f6d3ec4,0xbf80,0xbf6dbec4,0x3f35bf35,0xbec4bf6d,0xbf353f35,0x3ec43f6d,0x80003f80,0x3f6dbec4,0x8000bf80,0xbf6d3ec4,
0xbf35bf35,0xbec43f6d,0x3f353f35,0x3ec4bf6d,0x3f800000,0xbec4bf6d,0xbf800000,0x3ec43f6d,0xbf353f35,0x3f6d3ec4,0x3f35bf35,0xbf6dbec4,
0x3f800000,0xbec4bf6d,0xbf800000,0x3ec43f6d,0xbf353f35,0x3f6d3ec4,0x3f35bf35,0xbf6dbec4,0xbf80,0xbf6d3ec4,0x3f80,0x3f6dbec4,
0x3f353f35,0x3ec4bf6d,0xbf35bf35,0xbec43f6d,0x80003f80,0x3ec4bf6d,0x8000bf80,0xbec43f6d,0xbf353f35,0x3f6dbec4,0x3f35bf35,0xbf6d3ec4,
0xbf800000,0x3f6d3ec4,0x3f800000,0xbf6dbec4,0xbf35bf35,0x3ec43f6d,0x3f353f35,0xbec4bf6d,0x3f800000,0xbf6dbec4,0xbf800000,0x3f6d3ec4,
0x3f353f35,0xbec4bf6d,0xbf35bf35,0x3ec43f6d,0x3f80,0x3ec4bf6d,0xbf80,0xbec43f6d,0xbf353f35,0x3f6dbec4,0x3f35bf35,0xbf6d3ec4,
0x80003f80,0x8000bf80,0x80003f80,0x8000bf80,0x80003f80,0x8000bf80,0x80003f80,0x8000bf80,0x80003f80,0x8000bf80,0x80003f80,0x8000bf80,
0x80003f80,0x8000bf80,0x80003f80,0x8000bf80,0x3f800000,0xbf800000,0x3f800000,0xbf800000,0x3f800000,0xbf800000,0x3f800000,0xbf800000,
0x3f800000,0xbf800000,0x3f800000,0xbf800000,0x3f800000,0xbf800000,0x3f800000,0xbf800000,0x80003f80,0xbf35bf35,0x80003f80,0xbf35bf35,
0x3f800000,0xbf353f35,0x3f800000,0xbf353f35,0x8000bf80,0x3f353f35,0x8000bf80,0x3f353f35,0xbf800000,0x3f35bf35,0xbf800000,0x3f35bf35,
0x3f800000,0xbf353f35,0x3f800000,0xbf353f35,0xbf80,0x3f353f35,0xbf80,0x3f353f35,0xbf800000,0x3f35bf35,0xbf800000,0x3f35bf35,
0x3f80,0xbf35bf35,0x3f80,0xbf35bf35,0x80003f80,0xbf800000,0x80003f80,0xbf800000,0x8000bf80,0x3f800000,0x8000bf80,0x3f800000,
0x80003f80,0xbf800000,0x80003f80,0xbf800000,0x8000bf80,0x3f800000,0x8000bf80,0x3f800000,0x3f800000,0x3f80,0x3f800000,0x3f80,
0xbf800000,0xbf80,0xbf800000,0xbf80,0x3f800000,0x3f80,0x3f800000,0x3f80,0xbf800000,0xbf80,0xbf800000,0xbf80,
0x80003f80,0xbf353f35,0x80003f80,0xbf353f35,0xbf800000,0xbf35bf35,0xbf800000,0xbf35bf35,0x8000bf80,0x3f35bf35,0x8000bf80,0x3f35bf35,
0x3f800000,0x3f353f35,0x3f800000,0x3f353f35,0x3f800000,0x3f353f35,0x3f800000,0x3f353f35,0x3f80,0xbf353f35,0x3f80,0xbf353f35,
0xbf800000,0xbf35bf35,0xbf800000,0xbf35bf35,0xbf80,0x3f35bf35,0xbf80,0x3f35bf35,0x80003f80,0xbec4bf6d,0x8000bf80,0x3ec43f6d,
0x3f353f35,0xbf6dbec4,0xbf35bf35,0x3f6d3ec4,0x3f800000,0xbf6d3ec4,0xbf800000,0x3f6dbec4,0x3f35bf35,0xbec43f6d,0xbf353f35,0x3ec4bf6d,
0x3f800000,0xbf6d3ec4,0xbf800000,0x3f6dbec4,0x3f35bf35,0xbec43f6d,0xbf353f35,0x3ec4bf6d,0xbf80,0x3ec43f6d,0x3f80,0xbec4bf6d,
0xbf35bf35,0x3f6d3ec4,0x3f353f35,0xbf6dbec4,0x80003f80,0xbf6dbec4,0x8000bf80,0x3f6d3ec4,0x3f35bf35,0x3ec43f6d,0xbf353f35,0xbec4bf6d,
0xbf800000,0x3ec4bf6d,0x3f800000,0xbec43f6d,0x3f353f35,0xbf6d3ec4,0xbf35bf35,0x3f6dbec4,0x3f800000,0xbec43f6d,0xbf800000,0x3ec4bf6d,
0xbf35bf35,0x3f6dbec4,0x3f353f35,0xbf6d3ec4,0x3f80,0xbf6dbec4,0xbf80,0x3f6d3ec4,0x3f35bf35,0x3ec43f6d,0xbf353f35,0xbec4bf6d,
0x80003f80,0xbf6d3ec4,0x8000bf80,0x3f6dbec4,0xbf35bf35,0x3ec4bf6d,0x3f353f35,0xbec43f6d,0x3f800000,0x3ec43f6d,0xbf800000,0xbec4bf6d,
0xbf353f35,0xbf6dbec4,0x3f35bf35,0x3f6d3ec4,0x3f800000,0x3ec43f6d,0xbf800000,0xbec4bf6d,0xbf353f35,0xbf6dbec4,0x3f35bf35,0x3f6d3ec4,
0xbf80,0x3f6dbec4,0x3f80,0xbf6d3ec4,0x3f353f35,0xbec43f6d,0xbf35bf35,0x3ec4bf6d,0x80003f80,0xbec43f6d,0x8000bf80,0x3ec4bf6d,
0xbf353f35,0xbf6d3ec4,0x3f35bf35,0x3f6dbec4,0xbf800000,0xbf6dbec4,0x3f800000,0x3f6d3ec4,0xbf35bf35,0xbec4bf6d,0x3f353f35,0x3ec43f6d,
0x3f800000,0x3f6d3ec4,0xbf800000,0xbf6dbec4,0x3f353f35,0x3ec43f6d,0xbf35bf35,0xbec4bf6d,0x3f80,0xbec43f6d,0xbf80,0x3ec4bf6d,
0xbf353f35,0xbf6d3ec4,0x3f35bf35,0x3f6dbec4,
};
constexpr int TB_F = 0, TB_E = 512, TB_P2 = 1024;

enum { C_EP = 0, C_Z1 = 32, C_Z2 = 96, C_H3 = 128, C_U = 160, C_X = 256, C_TOTAL = 512 };
struct Scratch {
  unsigned cnt[C_TOTAL];
  uint32_t moda[8 * 2 * D_];
  uint32_t mod[4 * D_ + 256];
  uint32_t z1[120 * 5120];
  uint32_t z2[128 * 4800];
  uint32_t x1[S_ * D_ / 2];
  uint8_t h3[32 * 18 * 4096];
  uint8_t u[72 * D_ * 128];
  uint4 part[128 * 1152];
};
__device__ __align__(1024) Scratch g_s;

#define PF2 8
#define PF2K 16
#define HOLDA 3
#define GOAT 1
#define HOLD1 0
#define HW bulk_commit_wait
#define H3W 0
#define X1K 10
#define PEEK 1
#define H3G 2
#define PFF 2
#define NG1 2

#define FAILCNT(k) do {} while (0)
#define CK(k) do {} while (0)
#define CKX(k) do {} while (0)
#define TS(k) do {} while (0)
#define TSC(k) do {} while (0)
struct Maps { CUtensorMap z1, z2[2], w1a, w1b, h3[2], w2, x1, out, wf[4], wm; };
struct Params {
  const __nv_bfloat16 *x, *c, *wmod;
  Scratch* s;
  const uint4* tab;
  const __nv_bfloat16 *wr, *wi, *w1, *w2, *b1, *b2;
};

__device__ __forceinline__ uint32_t smem_u32(const void* p) { return (uint32_t)__cvta_generic_to_shared(p); }
__device__ __forceinline__ void mbar_init(uint32_t b, int c) { asm volatile("mbarrier.init.shared::cta.b64 [%0], %1;" ::"r"(b), "r"(c)); }
__device__ __forceinline__ void mbar_expect(uint32_t b, int bytes) { asm volatile("mbarrier.arrive.expect_tx.shared::cta.b64 _, [%0], %1;" ::"r"(b), "r"(bytes) : "memory"); }
__device__ __forceinline__ void mbar_arrive(uint32_t b) { asm volatile("mbarrier.arrive.shared::cta.b64 _, [%0];" ::"r"(b) : "memory"); }
#define MBAR_WAIT(SEM)                                                                                                         \
  asm volatile("{\n.reg .pred p;\n.reg .u32 it;\nmov.u32 it, 0;\nW:\nmbarrier.try_wait.parity" SEM ".shared::cta.b64 p, [%0], %1;\n" \
               "@p bra.uni D;\nadd.u32 it, it, 1;\nsetp.lt.u32 p, it, 0x400000;\n@p bra.uni W;\ntrap;\nD:\n}" ::"r"(b), "r"(ph) : "memory")
__device__ __forceinline__ void mbar_wait(uint32_t b, int ph) { MBAR_WAIT(""); }
__device__ __forceinline__ uint32_t mbar_test(uint32_t b, int ph) {
  uint32_t ok;
  asm volatile("{\n.reg .pred p;\nmbarrier.test_wait.parity.shared::cta.b64 p, [%1], %2;\nselp.u32 %0, 1, 0, p;\n}\n" : "=r"(ok) : "r"(b), "r"(ph) : "memory");
  return ok;
}
__device__ __forceinline__ void tma2d(uint32_t dst, const CUtensorMap* m, int c0, int c1, uint32_t bar) {
  asm volatile("cp.async.bulk.tensor.2d.shared::cluster.global.mbarrier::complete_tx::bytes [%0], [%1, {%3, %4}], [%2];" ::"r"(dst), "l"(m), "r"(bar), "r"(c0), "r"(c1) : "memory");
}
__device__ __forceinline__ uint64_t pol_ef() { uint64_t p; asm("createpolicy.fractional.L2::evict_first.b64 %0, 1.0;" : "=l"(p)); return p; }
__device__ __forceinline__ void tma3d_ef(uint32_t dst, const CUtensorMap* m, int c1, int c2, uint32_t bar) {
  asm volatile("cp.async.bulk.tensor.3d.shared::cluster.global.mbarrier::complete_tx::bytes.L2::cache_hint [%0], [%1, {%3, %4, %5}], [%2], %6;" ::"r"(dst), "l"(m), "r"(bar), "r"(0), "r"(c1), "r"(c2), "l"(pol_ef()) : "memory");
}
__device__ __forceinline__ void tma4d_ef(uint32_t dst, const CUtensorMap* m, int c1, int c2, int c3, uint32_t bar) {
  asm volatile("cp.async.bulk.tensor.4d.shared::cluster.global.mbarrier::complete_tx::bytes.L2::cache_hint [%0], [%1, {%3, %7, %4, %5}], [%2], %6;" ::"r"(dst), "l"(m), "r"(bar), "r"(0), "r"(c2), "r"(c3), "l"(pol_ef()), "r"(c1) : "memory");
}
__device__ __forceinline__ void bulk_ld(uint32_t dst, const void* src, int bytes, uint32_t bar) {
  asm volatile("cp.async.bulk.shared::cluster.global.mbarrier::complete_tx::bytes [%0], [%1], %2, [%3];" ::"r"(dst), "l"(src), "r"(bytes), "r"(bar) : "memory");
}
__device__ __forceinline__ void bulk_st(void* dst, uint32_t src, int bytes) {
  asm volatile("cp.async.bulk.global.shared::cta.bulk_group [%0], [%1], %2;" ::"l"(dst), "r"(src), "r"(bytes) : "memory");
}
__device__ __forceinline__ void tma_st2d(const CUtensorMap* m, uint32_t src, int c0, int c1) {
  asm volatile("cp.async.bulk.tensor.2d.global.shared::cta.bulk_group [%0, {%2, %3}], [%1];" ::"l"(m), "r"(src), "r"(c0), "r"(c1) : "memory");
}
__device__ __forceinline__ void tma_st3d(const CUtensorMap* m, uint32_t src, int c0, int c1, int c2) {
  asm volatile("cp.async.bulk.tensor.3d.global.shared::cta.bulk_group [%0, {%2, %3, %4}], [%1];" ::"l"(m), "r"(src), "r"(c0), "r"(c1), "r"(c2) : "memory");
}
__device__ __forceinline__ void bulk_commit_wait_read() {
  asm volatile("cp.async.bulk.commit_group;" ::: "memory");
  asm volatile("cp.async.bulk.wait_group.read 0;" ::: "memory");
}
__device__ __forceinline__ void bulk_commit_wait() {
  asm volatile("cp.async.bulk.commit_group;" ::: "memory");
  asm volatile("cp.async.bulk.wait_group 0;" ::: "memory");
}
__device__ __forceinline__ void prefetch_l2(const void* p, int bytes) {
  asm volatile("cp.async.bulk.prefetch.L2.global [%0], %1;" ::"l"(p), "r"(bytes) : "memory");
}
__device__ __forceinline__ void wg_fence() { asm volatile("wgmma.fence.sync.aligned;" ::: "memory"); }
__device__ __forceinline__ void wg_commit() { asm volatile("wgmma.commit_group.sync.aligned;" ::: "memory"); }
template <int N> __device__ __forceinline__ void wg_wait() { asm volatile("wgmma.wait_group.sync.aligned %0;" ::"n"(N) : "memory"); }
template <int N> __device__ __forceinline__ void reg_fence(float (&d)[N]) {
#pragma unroll
  for (int i = 0; i < N; i++) asm volatile("" : "+f"(d[i])::"memory");
}
__device__ __forceinline__ void fence_async_smem() { asm volatile("fence.proxy.async.shared::cta;" ::: "memory"); }
__device__ __forceinline__ void fence_async_glb() { asm volatile("fence.proxy.async.global;" ::: "memory"); }
__device__ __forceinline__ uint32_t ld_rlx(const void* p) { uint32_t v; asm volatile("ld.relaxed.gpu.global.b32 %0, [%1];" : "=r"(v) : "l"(p) : "memory"); return v; }
__device__ __forceinline__ uint2 ld_rlx2(const void* p) { uint2 v; asm volatile("ld.relaxed.gpu.global.v2.b32 {%0,%1}, [%2];" : "=r"(v.x), "=r"(v.y) : "l"(p) : "memory"); return v; }
__device__ __forceinline__ uint4 ld_rlx4(const void* p) { uint4 v; asm volatile("ld.relaxed.gpu.global.v4.b32 {%0,%1,%2,%3}, [%4];" : "=r"(v.x), "=r"(v.y), "=r"(v.z), "=r"(v.w) : "l"(p) : "memory"); return v; }
__device__ __forceinline__ uint32_t ld_nc(const void* p) { uint32_t v; asm volatile("ld.global.nc.L1::no_allocate.b32 %0, [%1];" : "=r"(v) : "l"(p) : "memory"); return v; }
__device__ __forceinline__ uint4 ld_nc4(const void* p) { uint4 v; asm volatile("ld.global.nc.v4.b32 {%0,%1,%2,%3}, [%4];" : "=r"(v.x), "=r"(v.y), "=r"(v.z), "=r"(v.w) : "l"(p) : "memory"); return v; }
__device__ __forceinline__ uint32_t lds(uint32_t a) { uint32_t v; asm volatile("ld.shared.b32 %0, [%1];" : "=r"(v) : "r"(a) : "memory"); return v; }
__device__ __forceinline__ uint2 lds2(uint32_t a) { uint2 v; asm volatile("ld.shared.v2.b32 {%0,%1}, [%2];" : "=r"(v.x), "=r"(v.y) : "r"(a) : "memory"); return v; }
__device__ __forceinline__ uint4 lds4(uint32_t a) { uint4 v; asm volatile("ld.shared.v4.b32 {%0,%1,%2,%3}, [%4];" : "=r"(v.x), "=r"(v.y), "=r"(v.z), "=r"(v.w) : "r"(a) : "memory"); return v; }
__device__ __forceinline__ float lds_bf(uint32_t a) { uint32_t v; asm volatile("ld.shared.u16 %0, [%1];" : "=r"(v) : "r"(a) : "memory"); return __uint_as_float(v << 16); }
__device__ __forceinline__ void sts(uint32_t a, uint32_t v) { asm volatile("st.shared.b32 [%0], %1;" ::"r"(a), "r"(v) : "memory"); }
__device__ __forceinline__ void sts2(uint32_t a, uint32_t v0, uint32_t v1) { asm volatile("st.shared.v2.b32 [%0], {%1,%2};" ::"r"(a), "r"(v0), "r"(v1) : "memory"); }
__device__ __forceinline__ void sts4(uint32_t a, uint32_t v0, uint32_t v1, uint32_t v2, uint32_t v3) { asm volatile("st.shared.v4.b32 [%0], {%1,%2,%3,%4};" ::"r"(a), "r"(v0), "r"(v1), "r"(v2), "r"(v3) : "memory"); }
__device__ __forceinline__ void bar_sync(int id, int n) { asm volatile("bar.sync %0, %1;" ::"r"(id), "r"(n) : "memory"); }
__device__ __forceinline__ void bar_arrive(int id, int n) { asm volatile("bar.arrive %0, %1;" ::"r"(id), "r"(n) : "memory"); }
__device__ __forceinline__ void red_add(unsigned* p, unsigned v) { asm volatile("red.relaxed.gpu.global.add.u32 [%0], %1;" ::"l"(p), "r"(v) : "memory"); }
__device__ __forceinline__ bool any(bool p) { return __any_sync(0xffffffffu, p); }
constexpr int SPIN_MAX = 1 << 20;
__device__ __forceinline__ void wait_cnt(const unsigned* p, unsigned target) {
  int it = 0;
  while (any((int)(ld_rlx(p) - target) < 0) && ++it < SPIN_MAX) {}
}
__device__ __forceinline__ uint32_t pack_bf16(float lo, float hi) { uint32_t r; asm("cvt.rn.bf16x2.f32 %0, %1, %2;" : "=r"(r) : "f"(hi), "f"(lo)); return r; }
__device__ __forceinline__ float bf_lo(uint32_t v) { return __uint_as_float(v << 16); }
__device__ __forceinline__ float bf_hi(uint32_t v) { return __uint_as_float(v & 0xffff0000u); }
__device__ __forceinline__ uint32_t hadd2(uint32_t a, uint32_t b) { uint32_t r; asm("add.rn.bf16x2 %0, %1, %2;" : "=r"(r) : "r"(a), "r"(b)); return r; }
__device__ __forceinline__ uint32_t hmul2(uint32_t a, uint32_t b) { uint32_t r; asm("mul.rn.bf16x2 %0, %1, %2;" : "=r"(r) : "r"(a), "r"(b)); return r; }
__device__ __forceinline__ uint32_t hfma2(uint32_t a, uint32_t b, uint32_t c) { uint32_t r; asm("fma.rn.bf16x2 %0, %1, %2, %3;" : "=r"(r) : "r"(a), "r"(b), "r"(c)); return r; }
__device__ __forceinline__ float rbf(float x) { uint32_t r; asm("cvt.rn.bf16x2.f32 %0, %1, %2;" : "=r"(r) : "f"(x), "f"(0.0f)); return __uint_as_float(r); }
__device__ __forceinline__ void stmatrix4(uint32_t a, uint32_t r0, uint32_t r1, uint32_t r2, uint32_t r3) {
  asm volatile("stmatrix.sync.aligned.m8n8.x4.shared.b16 [%0], {%1,%2,%3,%4};" ::"r"(a), "r"(r0), "r"(r1), "r"(r2), "r"(r3) : "memory");
}
__device__ __forceinline__ void stmatrix2(uint32_t a, uint32_t r0, uint32_t r1) {
  asm volatile("stmatrix.sync.aligned.m8n8.x2.shared.b16 [%0], {%1,%2};" ::"r"(a), "r"(r0), "r"(r1) : "memory");
}
__device__ __forceinline__ void stmatrix4t(uint32_t a, uint32_t r0, uint32_t r1, uint32_t r2, uint32_t r3) {
  asm volatile("stmatrix.sync.aligned.m8n8.x4.trans.shared.b16 [%0], {%1,%2,%3,%4};" ::"r"(a), "r"(r0), "r"(r1), "r"(r2), "r"(r3) : "memory");
}
__device__ __forceinline__ uint32_t movm(uint32_t a) { uint32_t r; asm("movmatrix.sync.aligned.m8n8.trans.b16 %0, %1;" : "=r"(r) : "r"(a)); return r; }
template <bool ACC> __device__ __forceinline__ void mma16(float* d, uint32_t a0, uint32_t a1, uint32_t a2, uint32_t a3, uint32_t b0, uint32_t b1) {
  if (ACC) asm("mma.sync.aligned.m16n8k16.row.col.f32.bf16.bf16.f32 {%0,%1,%2,%3}, {%4,%5,%6,%7}, {%8,%9}, {%0,%1,%2,%3};"
               : "+f"(d[0]), "+f"(d[1]), "+f"(d[2]), "+f"(d[3]) : "r"(a0), "r"(a1), "r"(a2), "r"(a3), "r"(b0), "r"(b1));
  else asm("mma.sync.aligned.m16n8k16.row.col.f32.bf16.bf16.f32 {%0,%1,%2,%3}, {%4,%5,%6,%7}, {%8,%9}, {%10,%10,%10,%10};"
           : "=f"(d[0]), "=f"(d[1]), "=f"(d[2]), "=f"(d[3]) : "r"(a0), "r"(a1), "r"(a2), "r"(a3), "r"(b0), "r"(b1), "f"(0.f));
}
__device__ __forceinline__ uint32_t pin(uint32_t v) { uint32_t r; asm volatile("shfl.sync.bfly.b32 %0, %1, 0, 31, 0xffffffff;" : "=r"(r) : "r"(v)); return r; }
template <class T> __device__ __forceinline__ T* pin(T* p) {
  const uint64_t a = reinterpret_cast<uint64_t>(p);
  return reinterpret_cast<T*>((uint64_t)pin((uint32_t)a) | ((uint64_t)pin((uint32_t)(a >> 32)) << 32));
}
__device__ __forceinline__ uint32_t upin(uint32_t v) { return __shfl_sync(0xffffffffu, v, 0); }
template <class T> __device__ __forceinline__ T* upin(T* p) {
  const uint64_t a = reinterpret_cast<uint64_t>(p);
  return reinterpret_cast<T*>((uint64_t)upin((uint32_t)a) | ((uint64_t)upin((uint32_t)(a >> 32)) << 32));
}
__device__ __forceinline__ bool elect() {
  uint32_t p;
  asm volatile("{\n.reg .pred P;\nelect.sync _|P, 0xffffffff;\nselp.u32 %0, 1, 0, P;\n}" : "=r"(p));
  return p;
}
__device__ __forceinline__ uint32_t set_tag(uint32_t w, uint32_t tag) { uint32_t r; asm("lop3.b32 %0, %1, 0xfffffffe, %2, 0xea;" : "=r"(r) : "r"(w), "r"(tag)); return r; }
__device__ __forceinline__ uint32_t and_or(uint32_t w, uint32_t a, uint32_t o) { uint32_t r; asm("lop3.b32 %0, %1, %2, %3, 0xea;" : "=r"(r) : "r"(w), "r"(a), "r"(o)); return r; }
__device__ __forceinline__ uint32_t diff2(uint32_t a, uint32_t b, uint32_t tag) { uint32_t r; asm("lop3.b32 %0, %1, %2, %3, 0x7e;" : "=r"(r) : "r"(a), "r"(b), "r"(tag)); return r; }
__device__ __forceinline__ float2 cmul(float2 a, float2 b) { return make_float2(a.x * b.x - a.y * b.y, a.x * b.y + a.y * b.x); }

template<int TB> __device__ __forceinline__ void wgmma_ss_160_0(float (&d)[80], uint32_t al, uint32_t ah, uint32_t bl, uint32_t bh) {
  asm volatile("{\n.reg .b64 da, db;\nmov.b64 da, {%80, %81};\nmov.b64 db, {%82, %83};\n"
    "wgmma.mma_async.sync.aligned.m64n160k16.f32.bf16.bf16 {%0,%1,%2,%3,%4,%5,%6,%7,%8,%9,%10,%11,%12,%13,%14,%15,%16,%17,%18,%19,%20,%21,%22,%23,%24,%25,%26,%27,%28,%29,%30,%31,%32,%33,%34,%35,%36,%37,%38,%39,%40,%41,%42,%43,%44,%45,%46,%47,%48,%49,%50,%51,%52,%53,%54,%55,%56,%57,%58,%59,%60,%61,%62,%63,%64,%65,%66,%67,%68,%69,%70,%71,%72,%73,%74,%75,%76,%77,%78,%79}, da, db, 1, 1, 1, 1, %84;\n}\n"
    : "+f"(d[0]),"+f"(d[1]),"+f"(d[2]),"+f"(d[3]),"+f"(d[4]),"+f"(d[5]),"+f"(d[6]),"+f"(d[7]),"+f"(d[8]),"+f"(d[9]),"+f"(d[10]),"+f"(d[11]),"+f"(d[12]),"+f"(d[13]),"+f"(d[14]),"+f"(d[15]),"+f"(d[16]),"+f"(d[17]),"+f"(d[18]),"+f"(d[19]),"+f"(d[20]),"+f"(d[21]),"+f"(d[22]),"+f"(d[23]),"+f"(d[24]),"+f"(d[25]),"+f"(d[26]),"+f"(d[27]),"+f"(d[28]),"+f"(d[29]),"+f"(d[30]),"+f"(d[31]),"+f"(d[32]),"+f"(d[33]),"+f"(d[34]),"+f"(d[35]),"+f"(d[36]),"+f"(d[37]),"+f"(d[38]),"+f"(d[39]),"+f"(d[40]),"+f"(d[41]),"+f"(d[42]),"+f"(d[43]),"+f"(d[44]),"+f"(d[45]),"+f"(d[46]),"+f"(d[47]),"+f"(d[48]),"+f"(d[49]),"+f"(d[50]),"+f"(d[51]),"+f"(d[52]),"+f"(d[53]),"+f"(d[54]),"+f"(d[55]),"+f"(d[56]),"+f"(d[57]),"+f"(d[58]),"+f"(d[59]),"+f"(d[60]),"+f"(d[61]),"+f"(d[62]),"+f"(d[63]),"+f"(d[64]),"+f"(d[65]),"+f"(d[66]),"+f"(d[67]),"+f"(d[68]),"+f"(d[69]),"+f"(d[70]),"+f"(d[71]),"+f"(d[72]),"+f"(d[73]),"+f"(d[74]),"+f"(d[75]),"+f"(d[76]),"+f"(d[77]),"+f"(d[78]),"+f"(d[79])
    : "r"(al), "r"(ah), "r"(bl), "r"(bh), "n"(TB));
}
template<int TB> __device__ __forceinline__ void wgmma_ss_144_0(float (&d)[80], uint32_t al, uint32_t ah, uint32_t bl, uint32_t bh) {
  asm volatile("{\n.reg .b64 da, db;\nmov.b64 da, {%72, %73};\nmov.b64 db, {%74, %75};\n"
    "wgmma.mma_async.sync.aligned.m64n144k16.f32.bf16.bf16 {%0,%1,%2,%3,%4,%5,%6,%7,%8,%9,%10,%11,%12,%13,%14,%15,%16,%17,%18,%19,%20,%21,%22,%23,%24,%25,%26,%27,%28,%29,%30,%31,%32,%33,%34,%35,%36,%37,%38,%39,%40,%41,%42,%43,%44,%45,%46,%47,%48,%49,%50,%51,%52,%53,%54,%55,%56,%57,%58,%59,%60,%61,%62,%63,%64,%65,%66,%67,%68,%69,%70,%71}, da, db, 1, 1, 1, 1, %76;\n}\n"
    : "+f"(d[0]),"+f"(d[1]),"+f"(d[2]),"+f"(d[3]),"+f"(d[4]),"+f"(d[5]),"+f"(d[6]),"+f"(d[7]),"+f"(d[8]),"+f"(d[9]),"+f"(d[10]),"+f"(d[11]),"+f"(d[12]),"+f"(d[13]),"+f"(d[14]),"+f"(d[15]),"+f"(d[16]),"+f"(d[17]),"+f"(d[18]),"+f"(d[19]),"+f"(d[20]),"+f"(d[21]),"+f"(d[22]),"+f"(d[23]),"+f"(d[24]),"+f"(d[25]),"+f"(d[26]),"+f"(d[27]),"+f"(d[28]),"+f"(d[29]),"+f"(d[30]),"+f"(d[31]),"+f"(d[32]),"+f"(d[33]),"+f"(d[34]),"+f"(d[35]),"+f"(d[36]),"+f"(d[37]),"+f"(d[38]),"+f"(d[39]),"+f"(d[40]),"+f"(d[41]),"+f"(d[42]),"+f"(d[43]),"+f"(d[44]),"+f"(d[45]),"+f"(d[46]),"+f"(d[47]),"+f"(d[48]),"+f"(d[49]),"+f"(d[50]),"+f"(d[51]),"+f"(d[52]),"+f"(d[53]),"+f"(d[54]),"+f"(d[55]),"+f"(d[56]),"+f"(d[57]),"+f"(d[58]),"+f"(d[59]),"+f"(d[60]),"+f"(d[61]),"+f"(d[62]),"+f"(d[63]),"+f"(d[64]),"+f"(d[65]),"+f"(d[66]),"+f"(d[67]),"+f"(d[68]),"+f"(d[69]),"+f"(d[70]),"+f"(d[71])
    : "r"(al), "r"(ah), "r"(bl), "r"(bh), "n"(TB));
}
template<int TB> __device__ __forceinline__ void wgmma_ss_96_0(float (&d)[80], uint32_t al, uint32_t ah, uint32_t bl, uint32_t bh) {
  asm volatile("{\n.reg .b64 da, db;\nmov.b64 da, {%48, %49};\nmov.b64 db, {%50, %51};\n"
    "wgmma.mma_async.sync.aligned.m64n96k16.f32.bf16.bf16 {%0,%1,%2,%3,%4,%5,%6,%7,%8,%9,%10,%11,%12,%13,%14,%15,%16,%17,%18,%19,%20,%21,%22,%23,%24,%25,%26,%27,%28,%29,%30,%31,%32,%33,%34,%35,%36,%37,%38,%39,%40,%41,%42,%43,%44,%45,%46,%47}, da, db, 1, 1, 1, 1, %52;\n}\n"
    : "+f"(d[0]),"+f"(d[1]),"+f"(d[2]),"+f"(d[3]),"+f"(d[4]),"+f"(d[5]),"+f"(d[6]),"+f"(d[7]),"+f"(d[8]),"+f"(d[9]),"+f"(d[10]),"+f"(d[11]),"+f"(d[12]),"+f"(d[13]),"+f"(d[14]),"+f"(d[15]),"+f"(d[16]),"+f"(d[17]),"+f"(d[18]),"+f"(d[19]),"+f"(d[20]),"+f"(d[21]),"+f"(d[22]),"+f"(d[23]),"+f"(d[24]),"+f"(d[25]),"+f"(d[26]),"+f"(d[27]),"+f"(d[28]),"+f"(d[29]),"+f"(d[30]),"+f"(d[31]),"+f"(d[32]),"+f"(d[33]),"+f"(d[34]),"+f"(d[35]),"+f"(d[36]),"+f"(d[37]),"+f"(d[38]),"+f"(d[39]),"+f"(d[40]),"+f"(d[41]),"+f"(d[42]),"+f"(d[43]),"+f"(d[44]),"+f"(d[45]),"+f"(d[46]),"+f"(d[47])
    : "r"(al), "r"(ah), "r"(bl), "r"(bh), "n"(TB));
}
template<int TB> __device__ __forceinline__ void wgmma_ss_48_48(float (&d)[80], uint32_t al, uint32_t ah, uint32_t bl, uint32_t bh) {
  asm volatile("{\n.reg .b64 da, db;\nmov.b64 da, {%24, %25};\nmov.b64 db, {%26, %27};\n"
    "wgmma.mma_async.sync.aligned.m64n48k16.f32.bf16.bf16 {%0,%1,%2,%3,%4,%5,%6,%7,%8,%9,%10,%11,%12,%13,%14,%15,%16,%17,%18,%19,%20,%21,%22,%23}, da, db, 1, 1, 1, 1, %28;\n}\n"
    : "+f"(d[48]),"+f"(d[49]),"+f"(d[50]),"+f"(d[51]),"+f"(d[52]),"+f"(d[53]),"+f"(d[54]),"+f"(d[55]),"+f"(d[56]),"+f"(d[57]),"+f"(d[58]),"+f"(d[59]),"+f"(d[60]),"+f"(d[61]),"+f"(d[62]),"+f"(d[63]),"+f"(d[64]),"+f"(d[65]),"+f"(d[66]),"+f"(d[67]),"+f"(d[68]),"+f"(d[69]),"+f"(d[70]),"+f"(d[71])
    : "r"(al), "r"(ah), "r"(bl), "r"(bh), "n"(TB));
}
__device__ __forceinline__ void wgmma_rs_72(float (&d)[36], uint32_t a0, uint32_t a1, uint32_t a2, uint32_t a3, uint32_t bl, uint32_t bh, int sd) {
  asm volatile("{\n.reg .pred p;\n.reg .b64 db;\nsetp.ne.b32 p, %42, 0;\nmov.b64 db, {%40, %41};\n"
    "wgmma.mma_async.sync.aligned.m64n72k16.f32.bf16.bf16 {%0,%1,%2,%3,%4,%5,%6,%7,%8,%9,%10,%11,%12,%13,%14,%15,%16,%17,%18,%19,%20,%21,%22,%23,%24,%25,%26,%27,%28,%29,%30,%31,%32,%33,%34,%35}, {%36,%37,%38,%39}, db, p, 1, 1, 1;\n}\n"
    : "+f"(d[0]),"+f"(d[1]),"+f"(d[2]),"+f"(d[3]),"+f"(d[4]),"+f"(d[5]),"+f"(d[6]),"+f"(d[7]),"+f"(d[8]),"+f"(d[9]),"+f"(d[10]),"+f"(d[11]),"+f"(d[12]),"+f"(d[13]),"+f"(d[14]),"+f"(d[15]),"+f"(d[16]),"+f"(d[17]),"+f"(d[18]),"+f"(d[19]),"+f"(d[20]),"+f"(d[21]),"+f"(d[22]),"+f"(d[23]),"+f"(d[24]),"+f"(d[25]),"+f"(d[26]),"+f"(d[27]),"+f"(d[28]),"+f"(d[29]),"+f"(d[30]),"+f"(d[31]),"+f"(d[32]),"+f"(d[33]),"+f"(d[34]),"+f"(d[35])
    : "r"(a0), "r"(a1), "r"(a2), "r"(a3), "r"(bl), "r"(bh), "r"(sd));
}
__device__ __forceinline__ void wgmma_rs_48(float (&d)[24], uint32_t a0, uint32_t a1, uint32_t a2, uint32_t a3, uint32_t bl, uint32_t bh, int sd) {
  asm volatile("{\n.reg .pred p;\n.reg .b64 db;\nsetp.ne.b32 p, %30, 0;\nmov.b64 db, {%28, %29};\n"
    "wgmma.mma_async.sync.aligned.m64n48k16.f32.bf16.bf16 {%0,%1,%2,%3,%4,%5,%6,%7,%8,%9,%10,%11,%12,%13,%14,%15,%16,%17,%18,%19,%20,%21,%22,%23}, {%24,%25,%26,%27}, db, p, 1, 1, 1;\n}\n"
    : "+f"(d[0]),"+f"(d[1]),"+f"(d[2]),"+f"(d[3]),"+f"(d[4]),"+f"(d[5]),"+f"(d[6]),"+f"(d[7]),"+f"(d[8]),"+f"(d[9]),"+f"(d[10]),"+f"(d[11]),"+f"(d[12]),"+f"(d[13]),"+f"(d[14]),"+f"(d[15]),"+f"(d[16]),"+f"(d[17]),"+f"(d[18]),"+f"(d[19]),"+f"(d[20]),"+f"(d[21]),"+f"(d[22]),"+f"(d[23])
    : "r"(a0), "r"(a1), "r"(a2), "r"(a3), "r"(bl), "r"(bh), "r"(sd));
}
template<int N,int OFF,int TB> __device__ __forceinline__ void wgmma_ss(float (&d)[80], uint32_t al, uint32_t ah, uint32_t bl, uint32_t bh) {
  if constexpr (N==160) wgmma_ss_160_0<TB>(d, al, ah, bl, bh);
  else if constexpr (N==144) wgmma_ss_144_0<TB>(d, al, ah, bl, bh);
  else if constexpr (N==96) wgmma_ss_96_0<TB>(d, al, ah, bl, bh);
  else if constexpr (N==48) wgmma_ss_48_48<TB>(d, al, ah, bl, bh);
}

__device__ __forceinline__ void dft3(float2& a, float2& b, float2& c) {
  const float s = 0.86602540378443864676f;
  float2 t = make_float2(b.x + c.x, b.y + c.y), d = make_float2(b.x - c.x, b.y - c.y);
  float2 m = make_float2(fmaf(-0.5f, t.x, a.x), fmaf(-0.5f, t.y, a.y));
  a = make_float2(a.x + t.x, a.y + t.y);
  b = make_float2(fmaf(s, d.y, m.x), fmaf(-s, d.x, m.y));
  c = make_float2(fmaf(-s, d.y, m.x), fmaf(s, d.x, m.y));
}
__device__ __forceinline__ void dft9(float2 (&x)[9]) {
  const float2 w1 = make_float2(0.76604444311897803520f, -0.64278760968653932632f);
  const float2 w2 = make_float2(0.17364817766693034885f, -0.98480775301220805937f);
  const float2 w4 = make_float2(-0.93969262078590838405f, -0.34202014332566873304f);
  dft3(x[0], x[3], x[6]); dft3(x[1], x[4], x[7]); dft3(x[2], x[5], x[8]);
  x[4] = cmul(x[4], w1); x[7] = cmul(x[7], w2); x[5] = cmul(x[5], w2); x[8] = cmul(x[8], w4);
  dft3(x[0], x[1], x[2]); dft3(x[3], x[4], x[5]); dft3(x[6], x[7], x[8]);
  float2 t;
  t = x[1]; x[1] = x[3]; x[3] = t;
  t = x[2]; x[2] = x[6]; x[6] = t;
  t = x[5]; x[5] = x[7]; x[7] = t;
}

__device__ __forceinline__ uint32_t* mod_ptr(Scratch* sc, int u, int t128) {
  const int i = t128 & 15;
  return u < 72 ? sc->moda + (t128 >> 4) * (2 * D_) + 16 * u + 2 * (i & 7) + (i >> 3) : sc->mod + 16 * (u - 72) + i;
}
__device__ __forceinline__ void mod_unit(Scratch* sc, int u, int t128, uint32_t sw_, uint32_t bar, int ph, uint32_t rb, uint32_t tag) {
  const int w = t128 >> 5, l = t128 & 31;
  uint32_t b[18];
#pragma unroll
  for (int i = 0; i < 18; i++) b[i] = lds(red + 512 + (72 * w + 4 * i + (l & 3)) * 4);
  const uint32_t sa = pin(sw_ + (144 * w + (l & 7) + 8 * (l >> 4)) * 32 + (((l >> 3) ^ (l >> 2)) & 1) * 16);
  const uint32_t sr = pin(rb + (l >> 2) * 16 + w * 4);
  uint32_t* const dst = pin(mod_ptr(sc, u, t128));
  const int kind = u / 36;
  const float mul = __uint_as_float(pin(__float_as_uint(kind == 0 ? 16.0f : 1.0f))), add = __uint_as_float(pin(__float_as_uint(kind == 1 || kind == 4 ? 1.0f : 0.0f)));
  mbar_wait(bar, ph);
  if (t128 == 0 && u < 72) TS(10);
  float d[3][4];
#pragma unroll
  for (int i = 0; i < 9; i++) {
    uint32_t a0, a1, a2, a3;
    asm volatile("ldmatrix.sync.aligned.m8n8.x4.trans.shared.b16 {%0,%1,%2,%3}, [%4];" : "=r"(a0), "=r"(a1), "=r"(a2), "=r"(a3) : "r"(sa + i * 512) : "memory");
    if (i < 3) mma16<false>(d[i], a0, a1, a2, a3, b[2 * i], b[2 * i + 1]);
    else mma16<true>(d[i % 3], a0, a1, a2, a3, b[2 * i], b[2 * i + 1]);
  }
  if ((l & 3) == 0) { sts(sr, __float_as_uint(d[0][0] + d[1][0] + d[2][0])); sts(sr + 128, __float_as_uint(d[0][2] + d[1][2] + d[2][2])); }
  bar_sync(4, 128);
  const uint4 v = lds4(rb + (l & 15) * 16);
  const float m = rbf(fmaf(rbf((__uint_as_float(v.x) + __uint_as_float(v.y)) + (__uint_as_float(v.z) + __uint_as_float(v.w))), mul, add));
  if (u < 72 || t128 < 16) *dst = __float_as_uint(m) | tag;
}

__device__ __forceinline__ float rsq(float x) { float r; asm("rsqrt.approx.ftz.f32 %0, %1;" : "=f"(r) : "f"(x)); return r; }
__device__ __forceinline__ void ln_stats2(const float (&a)[18], const float (&b)[18], float sc, float& oa, float& ra, float& ob, float& rb) {
  float v[4] = {0.f, 0.f, 0.f, 0.f}, w[4] = {0.f, 0.f, 0.f, 0.f};
#pragma unroll
  for (int i = 0; i < 18; i += 2) {
    v[0] += a[i]; v[1] = fmaf(a[i], a[i], v[1]); v[2] += b[i]; v[3] = fmaf(b[i], b[i], v[3]);
    w[0] += a[i + 1]; w[1] = fmaf(a[i + 1], a[i + 1], w[1]); w[2] += b[i + 1]; w[3] = fmaf(b[i + 1], b[i + 1], w[3]);
  }
#pragma unroll
  for (int e = 0; e < 4; e++) v[e] += w[e];
#pragma unroll
  for (int o = 16; o; o >>= 1) {
#pragma unroll
    for (int e = 0; e < 4; e++) v[e] += __shfl_xor_sync(0xffffffffu, v[e], o);
  }
  const float ma = v[0] * (1.0f / D_), mb = v[2] * (1.0f / D_);
  ra = sc * rsq(fmaxf(fmaf(-ma, ma, v[1] * (1.0f / D_)), 0.f) + 1e-5f);
  rb = sc * rsq(fmaxf(fmaf(-mb, mb, v[3] * (1.0f / D_)), 0.f) + 1e-5f);
  oa = -ma * ra; ob = -mb * rb;
}

__device__ __forceinline__ float tmat(int c, int q, int j) {
  const int ph = q == 1 ? 1024 * j : (q >> 1) * (c + 128 * j) + 512 * (q & 1);
  return __cosf((float)(((ph + 1024) & 2047) - 1024) * (6.283185307179586f / 2048.0f));
}
__device__ __forceinline__ uint32_t line_off(int k1, int kap, int pi, int f) {
  int kd = 64 * k1 + 9 * kap;
  if (kap == 0 && k1 > 4) kd -= 288;
  if (kd >= D_) kd -= D_;
  return pi * 2400 + ((min(kd, D_ - kd) ^ f) << 3);
}

constexpr int JSK = 5;
struct Ring { uint32_t st, ph; };
template <bool G2, class T> __device__ __forceinline__ void ring_next(T& st, T& ph) {
  if (++st == NST) st = 0;
  ph ^= ((G2 ? 0xDu : 0x1u) >> st) & 1;
}
__device__ __forceinline__ void arrive_if(uint32_t a, uint32_t p) {
  asm volatile("{\n.reg .pred p;\nsetp.ne.u32 p, %1, 0;\n@p mbarrier.arrive.shared::cta.b64 _, [%0];\n}" ::"r"(a), "r"(p) : "memory");
}
template <int NA> __device__ __forceinline__ void reg_fence_n(float (&d)[80]) {
#pragma unroll
  for (int i = 0; i < NA; i++) asm volatile("" : "+f"(d[i])::"memory");
}
template <int MODE>
__device__ __forceinline__ void gemm_main(float (&acc)[80], uint32_t da0, uint32_t da1, uint32_t db0, uint32_t db1, int wg, Ring& rg,
                                          uint32_t* x1p, const uint32_t (&xr)[18]) {
  static_assert(JSK == NST - 1, "the held slot is the first one that is not refilled by GEMM1");
  constexpr int NKB = MODE == 3 ? 36 : 32;
  constexpr uint32_t HA = 0x40000040u, HB = MODE == 3 ? 0x40000040u : 0x80000020u;
  constexpr uint32_t KA = 2048 >> 4, KB = MODE == 3 ? (32 >> 4) : (1024 >> 4);
  constexpr int NA = MODE ? 72 : 80;
  const uint32_t t = threadIdx.x & 127;
  const uint32_t eb = full0 + 8 * NST;
  uint32_t pb = 0, rel = t == 0, prel = 0, ok = 0;
  int n = MODE == 3 ? NKB - JSK : X1K + 2 * wg;
#pragma unroll 1
  for (int pass = MODE == 3 ? 0 : -1;; pass++) {
#pragma unroll 1
    do {
      const uint32_t so = rg.st * (STAGE >> 4), cb = eb + 8 * rg.st;
      if (__builtin_expect(!ok, 0)) mbar_wait(full0 + 8 * rg.st, rg.ph);
      reg_fence_n<NA>(acc);
      wg_fence();
#pragma unroll
      for (int k = 0; k < 4; k++) {
        if (k == 3) { ring_next<MODE == 3>(rg.st, rg.ph); ok = PEEK ? mbar_test(full0 + 8 * rg.st, rg.ph) : 0; }
        if (MODE == 0) wgmma_ss<160, 0, 1>(acc, da0 + so + k * KA, HA, db0 + so + k * KB, HB);
        else if (MODE == 3) wgmma_ss<144, 0, 0>(acc, da0 + so + k * KA, HA, db0 + so + k * KB, HB);
        else {
          wgmma_ss<96, 0, 1>(acc, da0 + so + k * KA, HA, db0 + so + k * KB, HB);
          wgmma_ss<48, 48, 1>(acc, da1 + so + k * KA, HA, db1 + so + k * KB, HB);
        }
      }
      wg_commit();
      wg_wait<1>();
      reg_fence_n<NA>(acc);
      arrive_if(pb, prel);
      pb = cb; prel = rel;
    } while (--n);
    if (pass == 2 - wg) break;
    if (MODE != 3 && pass < 0) {
      if (blockIdx.x < 128) {
#pragma unroll
        for (int i = 0; i < 9; i++) { x1p[32 * i] = xr[i]; x1p[128 * 288 + 32 * i] = xr[9 + i]; }
      }
      n = NKB - JSK - X1K - 2 * wg;
      continue;
    }
    n = 1;
    if (pass == 0) {
      if (MODE != 3) prel = rel & wg;
      else rel = 0;
      n = JSK - 1 + wg;
      if (!wg) continue;
      wg_wait<0>();
      arrive_if(pb, prel);
      prel = 0;
    }
    bar_sync(1, 256);
  }
  wg_wait<0>();
  reg_fence_n<NA>(acc);
  if (MODE != 3) arrive_if(pb, prel & ~wg);
}

__device__ __forceinline__ float gelu_arg(float h) { return h * fmaf(8.0f * 0.044715f * 0.7978845608028654f, h * h, 2.0f * 0.7978845608028654f); }

__device__ __forceinline__ int kb2_order(int i) { const int wv = i / 6; return 6 * (i - 6 * wv) + ((0x431250 >> (4 * wv)) & 7); }

__device__ __forceinline__ void wait_flags(const unsigned* base, int n, int idx, unsigned target, uint64_t& ready) {
  if ((ready >> idx) & 1) return;
  const int l = threadIdx.x & 31;
  int it = 0;
  while (true) {
    unsigned a = ld_rlx(base + l), b = l + 32 < n ? ld_rlx(base + l + 32) : target;
    ready = (uint64_t)__ballot_sync(0xffffffffu, (int)(a - target) >= 0) | ((uint64_t)__ballot_sync(0xffffffffu, (int)(b - target) >= 0) << 32);
    if (((ready >> idx) & 1) || ++it > SPIN_MAX) break;
  }
}

enum { B_FULL = 0, B_EMPTY = 6, B_S4 = 12, B_S5, B_LAND, B_FLT = B_LAND + 6, B_Z1, B_Z2, B_GO, B_X, B_WM, B_NUM, B_W0 = B_NUM };

__global__ void __launch_bounds__(NTHR, 1)
fused_kernel(const Params p, const __grid_constant__ Maps maps) {
  extern __shared__ __align__(1024) uint8_t smem_raw[];
  const int tid = threadIdx.x, cta = blockIdx.x, t128 = tid & 127;
  const int wp = __shfl_sync(0xffffffffu, tid >> 5, 0), wg = wp >> 2;
  const int l = tid & 31, g = l >> 2, t = l & 3;
  Scratch* const sc = p.s;
  const bool rows = cta < 128;
  const int R = cta - 12;

  uint32_t xr[18];
  uint32_t cv[3];
  const unsigned ep = ld_rlx(&sc->cnt[C_EP]) + 1;
  if (tid == 0) TS(0);
  if (wg == 2) {
#pragma unroll
    for (int i = 0; i < 3; i++) cv[i] = ld_nc(reinterpret_cast<const uint32_t*>(p.c) + min(t128 + 128 * i, 287));
    if (wp == 9 && l < 9 && rows) {
      const int h = 9 * cta + l;
      prefetch_l2(reinterpret_cast<const uint8_t*>(p.wmod) + (size_t)(h >> 1) * (12 * D_) + (h & 1) * (2 * D_), 2 * D_);
    }
    if (tid == 256 && cta < 72) {
      mbar_init(full0 + 8 * B_W0, 1);
      fence_async_smem();
      mbar_expect(full0 + 8 * B_W0, 18432);
#pragma unroll 1
      for (int i = 0; i < 3; i++) tma2d(sbase + O_P2 + i * 6144, &maps.wm, 16 * cta, 192 * i, full0 + 8 * B_W0);
    }
    __syncwarp();
#pragma unroll 1
    for (int u = cta < 72 ? cta : 72 + cta; u < 216; u += u < 72 ? 72 : NCTA) if (u < 72 || t128 < 16) *mod_ptr(sc, u, t128) = 0;
    if (wp == 11 && smem_u32(smem_raw) != sbase) __trap();
    if (wp >= 10 && elect()) {
#pragma unroll 1
      for (int i = wp - 10; i < B_NUM; i += 2) mbar_init(full0 + 8 * i, i == B_FLT ? 4 : i == B_WM ? 3 : i < B_LAND ? 2 : 1);
      fence_async_smem();
    }
    __syncwarp();
  }
  CK(0);
  auto load_x = [&]() {
    const uint32_t* xs = reinterpret_cast<const uint32_t*>(p.x) + (size_t)(cta + 256 * wp) * 288 + l;
#pragma unroll
    for (int i = 0; i < 9; i++) { xr[i] = ld_nc(xs + 32 * i); xr[9 + i] = ld_nc(xs + 128 * 288 + 32 * i); }
  };
  if (rows && wg < 2) load_x();
  if (tid == 64 && cta == NCTA - 1) prefetch_l2(p.tab, sizeof(T_TAB));
  __syncwarp();
  const uint32_t tag16 = (ep & 0x7fffu) | 0x8000u, tag1 = ep & 1u;

  if (wg == 2) {
#pragma unroll
    for (int i = 0; i < 3; i++) {
      const float c0 = bf_lo(cv[i]), c1 = bf_hi(cv[i]);
      sts(red + 512 + min(t128 + 128 * i, 287) * 4, pack_bf16(__fdividef(c0, 1.0f + __expf(-c0)), __fdividef(c1, 1.0f + __expf(-c1))));
    }
    if (wp == 9 && l < 14) asm volatile("prefetch.tensormap [%0];" ::"l"(&maps.z1 + l) : "memory");
    bar_sync(4, 128);
    if (cta < 72) {
      mod_unit(sc, cta, t128, sbase + O_P2, full0 + 8 * B_W0, 0, red, tag16);
      if (t128 == 0) TS(25);
    }
    CK(1);
  }
  const int pi = R / 15, col0 = 20 * (R - 15 * pi);
  const int xu = DF_ * pi + col0, xv = DF_ * (pi ? 16 - pi : 8) + col0;
  auto load_filter = [&](int a) {
    const int x = (a & 1) ? xv : xu;
    const bool wide = (x & 15) > 12;
    mbar_expect(full0 + 8 * B_FLT, wide ? 12288 : 8192);
    tma2d(sbase + O_RAW + a * 12288, &maps.wf[a & 2], x & ~15, 0, full0 + 8 * B_FLT);
    if (wide) tma2d(sbase + O_RAW + a * 12288 + 8192, &maps.wf[(a & 2) + 1], (x & ~15) + 32, 0, full0 + 8 * B_FLT);
  };
  const int kap = 8 * ((wp & 3) ^ (wg & 1)) + g;
  uint4 af[4];
  if (rows) {
    uint32_t tb[4];
#pragma unroll
    for (int i = 0; i < 4; i++) tb[i] = pack_bf16(tmat(cta, 8 * (i >> 1) + g, 2 * t + 8 * (i & 1)), tmat(cta, 8 * (i >> 1) + g, 2 * t + 8 * (i & 1) + 1));
    uint32_t sb1[3], lo[9];
#pragma unroll
    for (int i = 0; i < 4; i++) tb[i] = pin(tb[i]);
#pragma unroll
    for (int i = 0; i < 3; i++) {
      const int d = 48 * wp + 16 * i + (l & 15);
      sb1[i] = pin(sbase + O_B1 + (l >> 4) * 9216 + (d % 9) * 1024 + (d & 63) * 16);
    }
    const uint32_t snt = pin(sbase + O_NRM + ((l & 7) + 8 * (l >> 4)) * 1168 + (48 * wp + (l & 8)) * 2);
    uint2 ms[3], mc[3];
    const uint32_t smask = pin(t ? 0u : 0xffff0000u);
    const uint32_t* const mp = pin(sc->moda + (cta >> 4) * (2 * D_) + 48 * wp + 2 * g);
    auto load_mod = [&]() {
#pragma unroll
      for (int i = 0; i < 3; i++) { ms[i] = ld_rlx2(mp + 16 * i); mc[i] = ld_rlx2(mp + D_ + 16 * i); }
    };
    if (wg < 2) {
#pragma unroll
      for (int k1 = 0; k1 < 9; k1++) lo[k1] = pin(sbase + O_Z1 + line_off(k1, kap, 4 * wg + t, cta & 3));
      float a[18], b[18];
#pragma unroll
      for (int i = 0; i < 9; i++) { a[2 * i] = bf_lo(xr[i]); a[2 * i + 1] = bf_hi(xr[i]); b[2 * i] = bf_lo(xr[9 + i]); b[2 * i + 1] = bf_hi(xr[9 + i]); }
      float oa, ra, ob, rb;
      ln_stats2(a, b, 1.0f, oa, ra, ob, rb);
      CK(1);
      const uint32_t sn = sbase + O_NRM + wp * 2336 + l * 4;
#pragma unroll
      for (int i = 0; i < 9; i++) {
        sts(sn + i * 128, pack_bf16(fmaf(a[2 * i], ra, oa), fmaf(a[2 * i + 1], ra, oa)));
        sts(sn + 1168 + i * 128, pack_bf16(fmaf(b[2 * i], rb, ob), fmaf(b[2 * i + 1], rb, ob)));
      }
      CK(2);
      bar_arrive(10, NTHR);
      load_mod();
#pragma unroll
      for (int kk = 0; kk < 4; kk++) af[kk] = ld_nc4(p.tab + TB_F + kk * 128 + (t128 ^ (wg << 5)));
      bar_sync(1, 256);
      if (tid == 0) TS(2);
    } else {
      bar_sync(10, NTHR);
      load_mod();
      CK(2);
      if (PFF && wp >= 12 - PFF && elect()) prefetch_l2(reinterpret_cast<const uint8_t*>(wp == 10 ? p.wr : p.wi) + cta * 9248, 9248);
      __syncwarp();
    }
    float rs[3][8];
#pragma unroll
    for (int i = 0; i < 3; i++) {
      uint32_t a0, a1, a2, a3;
      asm volatile("ldmatrix.sync.aligned.m8n8.x4.trans.shared.b16 {%0,%1,%2,%3}, [%4];" : "=r"(a0), "=r"(a1), "=r"(a2), "=r"(a3)
                   : "r"(snt + 32 * i) : "memory");
      mma16<false>(&rs[i][0], a0, a1, a2, a3, tb[0], tb[1]);
      mma16<false>(&rs[i][4], a0, a1, a2, a3, tb[2], tb[3]);
    }
    CK(3);
    {
      int it = 0;
#pragma unroll 1
      while (true) {
        uint32_t bad = 0;
#pragma unroll
        for (int i = 0; i < 3; i++) bad |= diff2(ms[i].x, ms[i].y, tag16) | diff2(mc[i].x, mc[i].y, tag16);
        if (!any(bad & 0xffffu) || ++it > SPIN_MAX) break;
        load_mod();
      }
      CK(4);
      if (tid == 0) TS(3);
#pragma unroll
      for (int i = 0; i < 3; i++) {
        const float c0 = bf_hi(mc[i].x), c1 = bf_hi(mc[i].y);
        const float s0 = __uint_as_float(ms[i].x & smask), s1 = __uint_as_float(ms[i].y & smask);
        stmatrix4(sb1[i], pack_bf16(fmaf(rs[i][0], c0, s0), rs[i][1] * c0), pack_bf16(fmaf(rs[i][2], c1, s1), rs[i][3] * c1),
                  pack_bf16(rs[i][4] * c0, rs[i][5] * c0), pack_bf16(rs[i][6] * c1, rs[i][7] * c1));
      }
    }
    fence_async_smem();
    CK(5);
    if (wg == 2) {
      bar_arrive(5, NTHR);
      if (R >= 0 && elect()) load_filter(wp - 8);
      __syncwarp();
    } else {
      bar_sync(5, NTHR);
      CK(6);
      float acc[36];
      const uint32_t db = (((sbase + O_B1 + wg * 9216) & 0x3FFFF) >> 4) | ((128 >> 4) << 16);
      wg_fence();
#pragma unroll
      for (int kk = 0; kk < 4; kk++) wgmma_rs_72(acc, af[kk].x, af[kk].y, af[kk].z, af[kk].w, db + kk * 16, 1024 >> 4, kk);
      wg_commit();
      wg_wait<0>();
      reg_fence(acc);
      CK(7);
      float2 za[9], zb[9];
#pragma unroll
      for (int i = 0; i < 9; i++) { za[i] = make_float2(acc[4 * i], acc[4 * i + 2]); zb[i] = make_float2(acc[4 * i + 1], acc[4 * i + 3]); }
      dft9(za); dft9(zb);
      if (kap == 0) {
#pragma unroll
        for (int k = 1; k < 5; k++) {
          float2 a = za[k], b = za[9 - k];
          za[k] = make_float2(a.x + b.x, a.y - b.y); za[9 - k] = make_float2(a.y + b.y, b.x - a.x);
          a = zb[k]; b = zb[9 - k];
          zb[k] = make_float2(a.x + b.x, a.y - b.y); zb[9 - k] = make_float2(a.y + b.y, b.x - a.x);
        }
        sts2(lo[0] + 288 * 8, set_tag(pack_bf16(za[0].y, 0.f), tag1), pack_bf16(zb[0].y, 0.f));
        za[0].y = 0.f; zb[0].y = 0.f;
      }
      __syncwarp();
#pragma unroll
      for (int k1 = 0; k1 < 9; k1++) sts2(lo[k1], set_tag(pack_bf16(za[k1].x, za[k1].y), tag1), pack_bf16(zb[k1].x, zb[k1].y));
      fence_async_smem();
      CK(8);
      bar_arrive(2 + wg, 160);
      {
        const uint32_t fx = (((cta >> 4) ^ cta) & 3) << 3, dl = O_IN - O_Z1, st = sbase + O_ST + 15360 + tid * 16;
        sts4(st, (lo[0] ^ fx) + dl, (lo[1] ^ fx) + dl, (lo[2] ^ fx) + dl, (lo[3] ^ fx) + dl);
        sts4(st + 4096, (lo[4] ^ fx) + dl, (lo[5] ^ fx) + dl, (lo[6] ^ fx) + dl, (lo[7] ^ fx) + dl);
        sts4(st + 8192, (lo[8] ^ fx) + dl, (lo[0] ^ fx) + dl + (kap ? 0 : 288 * 8),
             sbase + O_B3 + wg * 1024 + (l >> 4) * 2048 + (2 * (kap & 24) + (l & 15)) * 16, 0);
      }
    }
    {
      uint32_t sy[6];
#pragma unroll
      for (int i = 0; i < 6; i++) {
        const int rr = 16 * (wp & 3) + g + 8 * (i & 1);
        sy[i] = sbase + O_Y + (t * 584 + 64 * ((3 * wg + (i >> 1) + 63 - rr) % 9) + rr) * 4;
      }
      sts4(sbase + O_ST + tid * 16, movm(tb[0]), movm(tb[2]), movm(tb[1]), movm(tb[3]));
      sts4(sbase + O_ST + 6144 + tid * 16, sy[0], sy[1], sy[2], sy[3]);
      sts2(sbase + O_ST + 12288 + tid * 8, sy[4], sy[5]);
    }
  } else {
    __syncthreads();
  }

  if ((wp >> 1) == 4) {
    if (rows) {
      const int slot = 4 * (cta & 7) + ((cta >> 4) & 3) + 32 * (2 * (cta >> 6) + ((cta >> 3) & 1));
      const uint32_t c0 = upin(40 * slot), c1 = upin(60 * (wp - 8)), src = upin(sbase + O_Z1 + (wp - 8) * 9600);
      const CUtensorMap* mp = upin(&maps.z1);
      unsigned* hint = pin(&sc->cnt[C_Z1 + 32 * (wp - 8)]);
      bar_sync(wp - 6, 160);
      if (elect()) {
        tma_st2d(mp, src, c0, c1);
        HW();
        red_add(hint, 1);
        if (wp == 8) TS(4);
      }
    } else {
      int it = 0;
      while (any((ld_rlx(sc->moda + 36 * l) ^ tag16) & 0xffffu) && ++it < SPIN_MAX) {}
      if (elect()) { load_filter(wp - 8); load_filter(wp - 6); }
    }
    __syncwarp();
  }
  auto load_wm = [&](int u) {
    if (wp > 8 && elect()) {
      mbar_expect(full0 + 8 * B_WM, 6144);
      tma2d(sbase + O_NRM + (wp - 9) * 6144, &maps.wm, 16 * u, 192 * (wp - 9), full0 + 8 * B_WM);
    }
    __syncwarp();
  };
  if (R >= 0) {
    const int nl = (col0 + wp < DF_) + (wg < 2 && col0 + wp + 12 < DF_);
    uint4 cf[2][4], G[4];
#pragma unroll
    for (int i = 0; i < 4; i++) {
      cf[0][i] = __ldg(p.tab + TB_P2 + i * 32 + l);
      cf[1][i] = __ldg(p.tab + TB_P2 + (pi ? i : 4 + i) * 32 + l);
      G[i] = __ldg(p.tab + TB_P2 + (8 + i) * 32 + l);
    }
    const uint32_t* zin = sc->z1 + (size_t)R * 5120;
    if (wp == 10) {
      const uint32_t* zu = upin(zin);
      if (elect()) mbar_expect(full0 + 8 * B_Z1, 20480);
      wait_cnt(&sc->cnt[C_Z1 + 32 * (pi >> 2)], 128 * ep);
      if (elect()) {
        bulk_ld(sbase + O_P2, zu, 20480, full0 + 8 * B_Z1);
        TS(12);
      }
      __syncwarp();
    }
    mbar_wait(full0 + 8 * B_FLT, 0);
    CK(9);
    float wn[16], wc[16];
#pragma unroll 1
    for (int ln = nl - 1; ln >= 0; ln--) {
      const int col = col0 + wp + 12 * ln, k2 = (57 * col) & 63;
      const bool cj = k2 > 32 || (k2 == 32 && col != 288);
      const float nr = ((col & 31) == 0 && col != 0 && col != 288 ? 0.5f : 1.0f) / ((float)S_ * D_), ni = cj ? -nr : nr;
#pragma unroll
      for (int i = 0; i < 16; i++) wn[i] = wc[i];
#pragma unroll
      for (int cl = 0; cl < 2; cl++) {
        const int v = cl ^ (cj && pi), e = ((v ? xv : xu) & 15) + wp + 12 * ln, sh = e < 32 ? 6 : 5;
        const uint32_t base = sbase + O_RAW + v * 12288 + (e < 32 ? 2 * e : 8192 - 64 + 2 * e), msk = e < 32 ? 0x30 : 0x10;
        const int dm = v ? (cj || pi ? -1 : 0) : 0;
#pragma unroll
        for (int tt = 0; tt < 4; tt++) {
          const int kc = g + 64 * (tt >> 1) + 16 * t + 8 * (tt & 1);
          uint32_t a = base + ((((cj ? -kc : kc) + dm) & 127) << sh);
          a ^= (a >> 3) & msk;
          wc[4 * tt + 2 * cl] = lds_bf(a) * nr; wc[4 * tt + 2 * cl + 1] = lds_bf(a + 24576) * ni;
        }
      }
    }
    const float al = __uint_as_float(pin((pi ? 0x3f800000u : 0u) + (l >> 5)));
    const uint32_t tagv = pin(tag1 + (l >> 5));
    CK(10);
    uint32_t off = pin(l * 160 + ((wp ^ (g & 3)) << 3));
    uint32_t offo = pin(sbase + O_P2 + 20480 + off - 64 * l), po = 3072;
    unsigned* hz2 = pin(&sc->cnt[C_Z2]);
    const uint32_t do2 = pin(12288 - 32 * l);
    const CUtensorMap* mz2 = upin(&maps.z2[wp == 0]);
    const uint32_t sz2 = upin(sbase + O_P2 + 20480 + (wp ? 0 : 12288)), cz2 = upin(40 * R + (wp ? 0 : 24));
    mbar_wait(full0 + 8 * B_Z1, 0);
    CK(11);
    if (tid == 0) TS(8);
    if (wg == 2) load_wm(72 + cta);
    uint2 v[4], v2[4];
    const uint32_t o2 = nl > 1 ? 96 : 0;
#pragma unroll
    for (int i = 0; i < 4; i++) { v[i] = lds2(sbase + O_P2 + off + i * 5120); v2[i] = lds2(sbase + O_P2 + off + o2 + i * 5120); }
    auto bad2 = [&]() {
      return any((diff2(v[0].x, v[1].x, tagv) | diff2(v[2].x, v[3].x, tagv) | diff2(v2[0].x, v2[1].x, tagv) | diff2(v2[2].x, v2[3].x, tagv)) << 31);
    };
    if (__builtin_expect(bad2() && nl, 0)) {
      FAILCNT(0);
      int it = 0;
      do {
#pragma unroll
        for (int i = 0; i < 4; i++) {
          v[i] = ld_rlx2(reinterpret_cast<const uint8_t*>(zin) + off + i * 5120);
          v2[i] = ld_rlx2(reinterpret_cast<const uint8_t*>(zin) + off + o2 + i * 5120);
        }
      } while (bad2() && ++it < SPIN_MAX);
    }
#pragma unroll 1
    for (int ln = 0; ln < nl; ln++, offo += do2, po = 2048) {
      float d[4][4];
      uint32_t A[8];
#pragma unroll
      for (int h = 0; h < 2; h++) {
        mma16<false>(d[2 * h], cf[0][0].x, cf[0][0].y, cf[0][0].z, cf[0][0].w, v[h].x, v[2 + h].x);
        mma16<false>(d[2 * h + 1], cf[1][0].x, cf[1][0].y, cf[1][0].z, cf[1][0].w, v[h].y, v[2 + h].y);
      }
      if (ln) { fence_async_smem(); bar_arrive(15, NTHR); }
#pragma unroll
      for (int h = 0; h < 2; h++)
#pragma unroll
        for (int L = 0; L < 2; L++) {
          const uint4 tw = cf[L][2 + h];
          const float* z = d[2 * h + L];
          const float2 z0 = cmul(make_float2(z[0], z[2]), make_float2(__uint_as_float(tw.x), __uint_as_float(tw.y)));
          const float2 z1 = cmul(make_float2(z[1], z[3]), make_float2(__uint_as_float(tw.z), __uint_as_float(tw.w)));
          A[4 * h + L] = pack_bf16(z0.x, z0.y); A[4 * h + 2 + L] = pack_bf16(z1.x, z1.y);
        }
#pragma unroll
      for (int tt = 0; tt < 4; tt++) {
        mma16<false>(d[tt], A[0], A[1], A[2], A[3], G[tt].x, G[tt].y);
        mma16<true>(d[tt], A[4], A[5], A[6], A[7], G[tt].z, G[tt].w);
      }
#pragma unroll
      for (int tt = 0; tt < 4; tt++) {
        const float ar = d[tt][0], aj = d[tt][1], br = d[tt][2], bj = d[tt][3];
        const float2 y1 = cmul(make_float2(fmaf(-al, bj, ar), fmaf(al, br, aj)), make_float2(wc[4 * tt], wc[4 * tt + 1]));
        const float2 y2 = cmul(make_float2(fmaf(al, ar, bj), fmaf(al, aj, -br)), make_float2(wc[4 * tt + 2], wc[4 * tt + 3]));
        A[2 * tt] = pack_bf16(fmaf(al, y2.x, y1.x), fmaf(-al, y2.y, -y1.y));
        A[2 * tt + 1] = pack_bf16(fmaf(al, y1.y, -y2.y), fmaf(al, y1.x, -y2.x));
      }
#pragma unroll
      for (int i = 0; i < 16; i++) wc[i] = wn[i];
#pragma unroll
      for (int i = 0; i < 4; i++) v[i] = v2[i];
#pragma unroll
      for (int tt = 0; tt < 4; tt++) {
        mma16<false>(d[tt], A[0], A[1], A[2], A[3], G[tt].x, G[tt].y);
        mma16<true>(d[tt], A[4], A[5], A[6], A[7], G[tt].z, G[tt].w);
      }
#pragma unroll
      for (int h = 0; h < 2; h++)
#pragma unroll
        for (int L = 0; L < 2; L++) {
          const uint4 tw = cf[L][2 + h];
          const float2 z0 = cmul(make_float2(d[2 * h][2 * L], d[2 * h][2 * L + 1]), make_float2(__uint_as_float(tw.x), __uint_as_float(tw.y)));
          const float2 z1 = cmul(make_float2(d[2 * h + 1][2 * L], d[2 * h + 1][2 * L + 1]), make_float2(__uint_as_float(tw.z), __uint_as_float(tw.w)));
          A[4 * h + 2 * L] = movm(pack_bf16(z0.x, z1.x)); A[4 * h + 2 * L + 1] = movm(pack_bf16(z0.y, z1.y));
        }
#pragma unroll
      for (int h = 0; h < 2; h++) {
        mma16<false>(d[0], cf[0][1].x, cf[0][1].y, cf[0][1].z, cf[0][1].w, A[4 * h], A[4 * h + 1]);
        mma16<false>(d[1], cf[1][1].x, cf[1][1].y, cf[1][1].z, cf[1][1].w, A[4 * h + 2], A[4 * h + 3]);
#pragma unroll
        for (int e = 0; e < 2; e++)
          sts2(offo + (2 * h + e) * po, set_tag(pack_bf16(d[0][e], d[0][2 + e]), tagv), pack_bf16(d[1][e], d[1][2 + e]));
      }
      CK(12 + ln);
    }
    fence_async_smem();
    if (nl < 2 && wp != 8) bar_arrive(15, NTHR);
    if (wp & 7) { if (wg < 2) bar_arrive(6, 256); }
    else {
      if (wp) bar_sync(15, NTHR); else bar_sync(6, 256);
      if (elect()) {
        tma_st2d(mz2, sz2, cz2, 0);
        HW();
        if (wp == 0) { red_add(hz2, 1); TS(9); }
      }
      __syncwarp();
    }
  }
  if (wg == 2) {
#pragma unroll 1
    for (int u = 72 + cta, k = 0; u < 216; u += NCTA, k ^= 1) {
      if (R < 0) { fence_async_smem(); bar_sync(4, 128); load_wm(u); }
      mod_unit(sc, u, t128, sbase + O_NRM, full0 + 8 * B_WM, k, red + 256 - 256 * k, tag16);
    }
    fence_async_smem();
    CK(13);
  }

  const int grp = cta / 11, m1 = cta - 11 * grp;
  const bool helper = (m1 & 3) == 3;
  const int f1 = 384 * grp + (helper ? 192 : 128) * (m1 >> 2);
  const int d1 = 160 * (m1 & 3), flip = m1 >= 7;
  const int a1bytes = helper ? 24576 : 16384;
  auto load_a1 = [&](int st, int kb) {
    mbar_expect(full0 + 8 * st, a1bytes);
    tma4d_ef(sbase + st * STAGE, helper ? &maps.w1b : &maps.w1a, 4 * (kb >> 3), 16 * (kb & 7), f1 >> 6, full0 + 8 * st);
  };

  if (rows) {
#pragma unroll
    for (int kk = 0; kk < 4; kk++) af[kk] = __ldg(p.tab + TB_E + kk * 128 + t128);
    const uint4 c0 = lds4(sbase + O_ST + tid * 16), c1 = lds4(sbase + O_ST + 6144 + tid * 16);
    const uint2 c2 = lds2(sbase + O_ST + 12288 + tid * 8);
    const uint32_t tb[4] = {c0.x, c0.y, c0.z, c0.w}, sy[6] = {c1.x, c1.y, c1.z, c1.w, c2.x, c2.y};
    const uint32_t l8 = pin(8 * l), syl = pin(sbase + O_Y + wp * 2336 + 8 * l);
    const uint32_t sh3 = pin(sbase + O_B3 + (wp >> 1) * 4608 + (l >> 4) * 256 + (wp & 1) * 128 + ((((l >> 2) ^ (2 * cta + (wp & 1))) & 3) << 4) + (l & 3) * 4);
    const bool htag = (((sh3 >> 2) ^ (2 * cta + (wp & 1))) & 7) == 0;
    const uint32_t ham = pin(htag ? ~1u : ~0u), hom = pin(htag ? tag1 : 0u);
    const int slot = 4 * (cta >> 4) + ((cta >> 1) & 3) + 32 * (2 * ((cta >> 3) & 1) + (cta & 1));
    const uint32_t* zin = sc->z2 + (size_t)slot * 4800;
    if (wg == 2) {
      {
        uint4 v[4];
        const int i3 = min(t128 + 384, 431);
        int it = 0;
        while (true) {
          uint32_t bad = 0;
#pragma unroll
          for (int k = 0; k < 4; k++) v[k] = ld_rlx4(sc->mod + 4 * (k < 3 ? t128 + 128 * k : i3));
#pragma unroll
          for (int k = 0; k < 4; k++) {
            v[k].x ^= tag16; v[k].y ^= tag16; v[k].z ^= tag16; v[k].w ^= tag16;
            bad |= v[k].x | v[k].y | v[k].z | v[k].w;
          }
          if (!any(bad & 0xffffu) || ++it > SPIN_MAX) break;
        }
#pragma unroll
        for (int k = 0; k < 4; k++) sts4(sbase + O_MOD + 16 * (k < 3 ? t128 + 128 * k : i3), v[k].x, v[k].y, v[k].z, v[k].w);
      }
      CK(14);
      bar_sync(10, NTHR);
      mbar_wait(full0 + 8 * B_Z2, 0);
      if (elect()) {
        load_a1(wp - 8, wp - 8);
        if (wp > 8 && wp - 8 < NG1) prefetch_l2(reinterpret_cast<const uint8_t*>(p.w1) + (size_t)(128 * (4 * ((wp - 8) >> 1) + (cta >> 5)) + 64 * (wp & 1) + 2 * (cta & 31)) * (2 * F_), 4 * F_);
      }
      __syncwarp();
    } else {
      const uint4 e0 = lds4(sbase + O_ST + 15360 + tid * 16), e1 = lds4(sbase + O_ST + 19456 + tid * 16), e2 = lds4(sbase + O_ST + 23552 + tid * 16);
      const uint32_t lo[9] = {e0.x, e0.y, e0.z, e0.w, e1.x, e1.y, e1.z, e1.w, e2.x}, lx = e2.y, sb3 = e2.z;
      bar_arrive(10, NTHR);
      CK(14);
      if (wp == 1) {
        const uint32_t* zu = upin(zin);
        if (elect()) mbar_expect(full0 + 8 * B_Z2, 19200);
        wait_cnt(&sc->cnt[C_Z2], 120 * ep);
        if (elect()) {
          bulk_ld(sbase + O_IN, zu, 19200, full0 + 8 * B_Z2);
          TS(14);
        }
        __syncwarp();
      }
      mbar_wait(full0 + 8 * B_Z2, 0);
      CK(15);
      if (tid == 0) TS(11);
      uint2 v[10];
      uint32_t bad = 0;
#pragma unroll
      for (int k1 = 0; k1 < 10; k1++) v[k1] = lds2(k1 < 9 ? lo[k1] : lx);
#pragma unroll
      for (int k1 = 0; k1 < 10; k1 += 2) bad |= diff2(v[k1].x, v[k1 + 1].x, tag1);
      if (__builtin_expect(any(bad << 31), 0)) {
        FAILCNT(1);
        int it = 0;
        do {
          bad = 0;
#pragma unroll
          for (int k1 = 0; k1 < 10; k1++) v[k1] = ld_rlx2(reinterpret_cast<const uint8_t*>(zin) + ((k1 < 9 ? lo[k1] : lx) - (sbase + O_IN)));
#pragma unroll
          for (int k1 = 0; k1 < 10; k1 += 2) bad |= diff2(v[k1].x, v[k1 + 1].x, tag1);
        } while (any(bad & 1) && ++it < SPIN_MAX);
      }
      float2 za[9], zb[9];
#pragma unroll
      for (int i = 0; i < 9; i++) { za[i] = make_float2(bf_lo(v[i].x), bf_hi(v[i].x)); zb[i] = make_float2(bf_lo(v[i].y), bf_hi(v[i].y)); }
      if (kap == 0) {
#pragma unroll
        for (int k = 1; k < 5; k++) {
          float2 a = za[k], b = za[9 - k];
          za[k] = make_float2(a.x - b.y, a.y + b.x); za[9 - k] = make_float2(a.x + b.y, b.x - a.y);
          a = zb[k]; b = zb[9 - k];
          zb[k] = make_float2(a.x - b.y, a.y + b.x); zb[9 - k] = make_float2(a.x + b.y, b.x - a.y);
        }
        za[0].y = bf_lo(v[9].x); zb[0].y = bf_lo(v[9].y);
      }
      __syncwarp();
      dft9(za); dft9(zb);
#pragma unroll
      for (int n = 0; n < 8; n += 2) {
        const int i0 = (9 - n) % 9, i1 = 8 - n;
        stmatrix4(sb3 + n * 2048, pack_bf16(za[i0].x, zb[i0].x), pack_bf16(za[i0].y, zb[i0].y), pack_bf16(za[i1].x, zb[i1].x), pack_bf16(za[i1].y, zb[i1].y));
      }
      stmatrix2(sb3 + 8 * 2048, pack_bf16(za[1].x, zb[1].x), pack_bf16(za[1].y, zb[1].y));
      fence_async_smem();
    }
    CK(16);
    __syncthreads();
    CK(17);
    float acc[24];
    const uint32_t db = (((sbase + O_B3 + wg * 6144) & 0x3FFFF) >> 4) | ((128 >> 4) << 16);
    wg_fence();
#pragma unroll
    for (int kk = 0; kk < 4; kk++) wgmma_rs_48(acc, af[kk].x, af[kk].y, af[kk].z, af[kk].w, db + kk * 16, 1024 >> 4, kk);
    wg_commit();
    uint32_t ga[9];
    uint2 sh[9], sw[9];
    if (wg < 2) {
#pragma unroll
      for (int i = 0; i < 9; i++) {
        const uint2 v = lds2(l8 + sbase + O_MOD + 256 * i);
        ga[i] = __byte_perm(v.x, v.y, 0x7632);
        sh[i] = lds2(l8 + sbase + O_MOD + 4 * D_ + 256 * i);
        sw[i] = lds2(l8 + sbase + O_MOD + 8 * D_ + 256 * i);
      }
    }
    wg_wait<0>();
    reg_fence(acc);
    CK(18);
#pragma unroll
    for (int i = 0; i < 3; i++) {
      const float* a = &acc[8 * i];
      const uint32_t a0 = pack_bf16(a[0], a[1]), a1 = pack_bf16(a[2], a[3]), a2 = pack_bf16(a[4], a[5]), a3 = pack_bf16(a[6], a[7]);
#pragma unroll
      for (int jh = 0; jh < 2; jh++) {
        float y[4];
        mma16<false>(y, a0, a1, a2, a3, tb[2 * jh], tb[2 * jh + 1]);
        sts(sy[2 * i] + jh * (4 * 584 * 4), pack_bf16(y[0], y[1]));
        sts(sy[2 * i + 1] + jh * (4 * 584 * 4), pack_bf16(y[2], y[3]));
      }
    }
    CK(19);
    if (wg == 2) bar_arrive(7, NTHR);
    else {
      bar_sync(7, NTHR);
      CK(20);
      float a[18], b[18];
#pragma unroll
      for (int i = 0; i < 9; i++) {
        const uint2 y = lds2(syl + 256 * i);
        xr[i] = hfma2(ga[i], __byte_perm(y.x, y.y, 0x5410), xr[i]);
        xr[9 + i] = hfma2(ga[i], __byte_perm(y.x, y.y, 0x7632), xr[9 + i]);
        a[2 * i] = bf_lo(xr[i]); a[2 * i + 1] = bf_hi(xr[i]); b[2 * i] = bf_lo(xr[9 + i]); b[2 * i + 1] = bf_hi(xr[9 + i]);
      }
      float oa, ra, ob, rb;
      ln_stats2(a, b, 1.0f, oa, ra, ob, rb);
      CK(21);
#pragma unroll
      for (int i = 0; i < 9; i++) {
        const float c0 = __uint_as_float(sw[i].x), c1 = __uint_as_float(sw[i].y), s0 = __uint_as_float(sh[i].x), s1 = __uint_as_float(sh[i].y);
        a[2 * i] = fmaf(fmaf(a[2 * i], ra, oa), c0, s0); a[2 * i + 1] = fmaf(fmaf(a[2 * i + 1], ra, oa), c1, s1);
        b[2 * i] = fmaf(fmaf(b[2 * i], rb, ob), c0, s0); b[2 * i + 1] = fmaf(fmaf(b[2 * i + 1], rb, ob), c1, s1);
      }
      ln_stats2(a, b, 0.5f, oa, ra, ob, rb);
      CK(22);
#pragma unroll
      for (int i = 0; i < 9; i++) {
        sts(sh3 + i * 512, and_or(pack_bf16(fmaf(a[2 * i], ra, oa), fmaf(a[2 * i + 1], ra, oa)), ham, hom));
        sts(sh3 + i * 512 + 64, and_or(pack_bf16(fmaf(b[2 * i], rb, ob), fmaf(b[2 * i + 1], rb, ob)), ham, hom));
      }
      fence_async_smem();
      if (wp == 0) CKX(0);
      if (wp < 2 * H3G) bar_arrive(8, 32 + 64 * H3G); else bar_arrive(9, 288 - 64 * H3G);
      CK(23);
    }
  } else __syncthreads();

  const bool g2 = cta < 130 && (cta >> 1) != 56;
  const int z2 = cta < 112 ? cta : cta - 2, r = z2 >> 6;
  const int s2 = 128 * ((z2 >> 2) & 15), d2 = 144 * (z2 & 3);
  constexpr int XST = (33 + 36 - JSK - 1) % NST;
  constexpr int ST0 = (32 - JSK - 1) % NST, ST1 = 31 % NST;

  if (wg == 2) {
    asm volatile("setmaxnreg.dec.sync.aligned.u32 40;");
    auto load_b = [&](bool second, int i, int st) {
      const uint32_t lb = full0 + 8 * (B_LAND + st), bytes = second ? 18432 : STAGE - a1bytes;
      mbar_expect(lb, bytes);
      bulk_ld(sbase + st * STAGE + (second ? 16384 : a1bytes),
              second ? sc->u + ((size_t)(36 * r + kb2_order(i)) * D_ + d2) * 128 : sc->h3 + ((size_t)(i * 18 + (d1 >> 5)) << 12), bytes, lb);
    };
    if (wp == 8) {
      int st = rows ? 4 : 0, ph = 1;
#pragma unroll 1
      for (int kb = st; kb < 32; kb++) {
        if (rows && (kb >> 1) == 2) mbar_wait(full0 + 8 * (B_S4 - 4 + kb), 0);
        mbar_wait(empty0 + 8 * st, ph);
        if (elect()) {
          load_a1(st, kb);
          if (kb >= PF2K && kb < PF2K + PF2 && g2)
            prefetch_l2(reinterpret_cast<const uint8_t*>(p.w2) + (size_t)(36 * r + kb2_order(kb - PF2K)) * 262144 + (z2 & 63) * 4096, 4096);
        }
        __syncwarp();
        ring_next<false>(st, ph);
      }
      if (g2) {
        st++;
#pragma unroll 1
        for (int i = 0; i < 36; i++) {
          if (i == HOLDA) mbar_wait(full0 + 8 * B_GO, 0);
          mbar_wait(empty0 + 8 * st, ph);
          if (elect()) {
            mbar_expect(full0 + 8 * st, 16384);
            tma3d_ef(sbase + st * STAGE, &maps.w2, 64 * (36 * r + kb2_order(i)), s2 >> 6, full0 + 8 * st);
          }
          __syncwarp();
          ring_next<true>(st, ph);
        }
      }
    } else if (wp >= 10) {
      const int sw = wp - 10;
      if (rows) {
        const CUtensorMap* mp = upin(&maps.h3[sw]);
        const uint32_t src = upin(sbase + O_B3 + sw * (H3G * 4608)), c0 = upin(64 * (cta & 15)), c1 = upin(18 * (cta >> 4)), c2 = upin(H3G * sw);
        unsigned* flag = pin(&sc->cnt[C_H3 + (cta >> 4) + 8 * sw]);
        bar_sync(8 + sw, sw ? 288 - 64 * H3G : 32 + 64 * H3G);
        if (!sw) CKX(1);
        if (sw) { mbar_wait(full0 + 8 * H3W, 0); CKX(7); }
        if (elect()) {
          tma_st3d(mp, src, c0, c1, c2);
          if (!sw) CKX(2);
          mbar_arrive(full0 + 8 * B_S4);
          bulk_commit_wait();
          if (!sw) CKX(3);
          red_add(flag, 1);
          mbar_arrive(full0 + 8 * B_S5);
          if (!sw) CKX(4);
          TS(sw ? 24 : 13);
        }
        __syncwarp();
      }
      if (sw && g2) {
        mbar_wait(full0 + 8 * 5, 0);
#pragma unroll 1
        for (int i = 0; i < 36; i++) { sc->part[z2 * 1152 + 32 * i + l] = make_uint4(tag1 ^ 1, 0, 0, 0); __nanosleep(100); }
        __syncwarp();
      }
      uint32_t lph = 0;
      auto check_tiles = [&](int n, int st, uint32_t o1, uint32_t d2nd) {
#pragma unroll 1
        for (int i = 0; i < n; i++) {
          const uint32_t a1 = sbase + st * STAGE + o1, a2 = a1 + d2nd, lb = full0 + 8 * (B_LAND + st);
          int it = 0;
          while (true) {
            mbar_wait(lb, (lph >> st) & 1);
            lph ^= 1u << st;
            uint32_t v[20], bad = 0;
#pragma unroll
            for (int k = 0; k < 20; k++) v[k] = lds(k < 12 ? a1 + k * 1024 : a2 + (k - 12) * 1024);
#pragma unroll
            for (int k = 0; k < 20; k += 2) bad |= diff2(v[k], v[k + 1], tag1);
            if (__builtin_expect(!any(bad << 31) || ++it > SPIN_MAX, 1)) break;
            FAILCNT(2 + (n == 36));
            fence_async_smem();
            __syncwarp();
            if (elect()) load_b(n == 36, i, st);
            __syncwarp();
          }
          if (elect()) mbar_arrive(full0 + 8 * st);
          if (++st == NST) st = 0;
        }
      };
      if (!sw) check_tiles(32, 0, a1bytes + l * 32 + (l >> 2) * 4, helper ? 4096 : 12288);
      const uint32_t stg = sbase + (sw ? ST1 : ST0) * STAGE;
      const int kbA = (f1 >> 6) + (helper ? 2 : 1) * (sw ^ flip), kbB = helper ? (f1 >> 6) + 1 : kbA;
      const int dB = helper ? d1 + 32 * sw : d1 + 96;
      uint8_t* const uA = upin(sc->u + ((size_t)kbA * D_ + d1) * 128);
      uint8_t* const uB = upin(sc->u + ((size_t)kbB * D_ + dB) * 128);
      unsigned* const fA = pin(&sc->cnt[C_U + kbA]);
      unsigned* const fB = pin(&sc->cnt[C_U + kbB]);
      bar_sync(11 + sw, 160);
      if (elect()) { bulk_st(uA, stg, 96 * 128); TS(sw ? 31 : 30); }
      __syncwarp();
      bar_sync(13 + sw, 160);
      if (elect()) {
        bulk_st(uB, stg + 96 * 128, helper ? 32 * 128 : 64 * 128);
        if (helper) bulk_st(uB + (64 - 16 * sw) * 128, stg + 128 * 128, 16 * 128);
        bulk_commit_wait();
        red_add(fA, 2);
        if (helper) red_add(fB, 1);
        mbar_arrive(empty0 + 8 * (sw ? ST1 : ST0));
        TS(sw ? 23 : 17);
        if (sw && rows) {
          asm volatile("fence.acq_rel.gpu;" ::: "memory");
          red_add(&sc->cnt[C_X], 1);
        }
      }
      __syncwarp();
      if (g2) {
        if (!sw) check_tiles(36, 3, 16384 + l * 32 + (4 * (g & 1) + (g >> 1)) * 4, 10240);
        else {
          __nanosleep(4000);
          wait_cnt(&sc->cnt[C_X], 128 * ep);
          if (elect()) { asm volatile("fence.acq_rel.gpu;" ::: "memory"); mbar_arrive(full0 + 8 * B_X); }
        }
      }
      __syncwarp();
    } else {
      uint64_t ready = 0;
      int st = 0, ph = 1;
#pragma unroll 1
      for (int kb = 0; kb < 32; kb++) {
        const uint8_t* src = upin(sc->h3 + ((size_t)(kb * 18 + (d1 >> 5)) << 12));
        const uint32_t dst = upin(sbase + st * STAGE + a1bytes), lb = full0 + 8 * (B_LAND + st);
        if (rows && (kb >> 1) == 2) mbar_wait(full0 + 8 * (B_S4 - 4 + kb), 0);
        mbar_wait(empty0 + 8 * st, ph);
        if (elect()) mbar_expect(lb, STAGE - a1bytes);
        wait_flags(sc->cnt + C_H3, 32, (kb & 7) + (kb < 8 * H3G ? 0 : 8), 16 * ep, ready);
        if (kb == 0) CKX(5);
        if (elect()) bulk_ld(dst, src, STAGE - a1bytes, lb);
        if (kb == 0) CKX(6);
        if (kb == 5) CKX(8);
        if (kb == 8 * H3G) CKX(9);
        ring_next<false>(st, ph);
      }
      if (g2) {
        ready = 0;
        st++;
#pragma unroll 1
        for (int i = 0; i < 36; i++) {
          const int kb = kb2_order(i);
          const uint8_t* src = upin(sc->u + ((size_t)(36 * r + kb) * D_ + d2) * 128);
          const uint32_t dst = upin(sbase + st * STAGE + 16384), lb = full0 + 8 * (B_LAND + st);
          mbar_wait(empty0 + 8 * st, ph);
          if (elect()) mbar_expect(lb, 18432);
          wait_flags(sc->cnt + C_U + 36 * r, 36, kb, 8 * ep, ready);
          if (elect()) {
            bulk_ld(dst, src, 18432, lb);
            if (i == GOAT) mbar_arrive(full0 + 8 * B_GO);
          }
          ring_next<true>(st, ph);
        }
        mbar_wait(full0 + 8 * B_X, 0);
        fence_async_glb();
        mbar_wait(empty0 + 8 * st, ph);
        if (elect()) {
          mbar_arrive(full0 + 8 * XST);
          mbar_expect(full0 + 8 * XST, 18432);
#pragma unroll 1
          for (int i = 0; i < 3; i++) tma2d(sbase + XST * STAGE + 18432 + i * 6144, &maps.x1, d2 + 48 * i, s2 + 64 * (r ^ 1), full0 + 8 * XST);
        }
        __syncwarp();
      }
    }
  } else {
    asm volatile("setmaxnreg.inc.sync.aligned.u32 232;");
    const int wgu = wg;
    constexpr uint32_t sb4 = sbase >> 4;
    const int w = wp & 3;
    Ring rg = {0, 0};
    uint32_t* const x1p = sc->x1 + (size_t)(cta + 256 * wp) * 288 + l;
    const uint32_t ad = pin(sbase + (wg ? ST1 : ST0) * STAGE + (8 * (l >> 4) + (l & 7)) * 128 + (((2 * w + ((l >> 3) & 1)) ^ (l & 7)) << 4));
    const uint32_t uam = pin(g == 2 * t ? 0xfffefffeu : ~0u), uom = pin(g == 2 * t ? tag1 * 0x10001u : 0u);
    float acc[80];
    constexpr uint32_t LA = (8192 >> 4) << 16, LB = (4096 >> 4) << 16;
    {
      const int fa = f1 + (helper ? 128 : 64) * (wg ^ flip) + 16 * w + g, fb = helper ? f1 + 64 + 16 * w + g : fa;
      const float a0 = 0.5f * __bfloat162float(p.b1[fa]), a1 = 0.5f * __bfloat162float(p.b1[fa + 8]);
      const float b0 = 0.5f * __bfloat162float(p.b1[fb]), b1 = 0.5f * __bfloat162float(p.b1[fb + 8]);
#pragma unroll
      for (int i = 0; i < 80; i++) acc[i] = i < 48 ? ((i & 2) ? a1 : a0) : ((i & 2) ? b1 : b0);
      reg_fence(acc);
    }
    if (!helper) gemm_main<0>(acc, sb4 + (wgu ^ flip) * 512 + LA, 0, sb4 + 1024 + LB, 0, wgu, rg, x1p, xr);
    else {
      float ac2[80];
#pragma unroll
      for (int i = 0; i < 72; i++) asm volatile("mov.b32 %0, %1;" : "=f"(ac2[i]) : "f"(acc[i]));
      gemm_main<1>(ac2, sb4 + (wgu ^ flip) * 1024 + LA, sb4 + 512 + LA, sb4 + 1536 + LB, sb4 + 1536 + (wgu ? 256 + LB + (2 << 16) : 2 * LB), wgu, rg, x1p, xr);
#pragma unroll
      for (int i = 0; i < 72; i++) asm volatile("mov.b32 %0, %1;" : "=f"(acc[i]) : "f"(ac2[i]));
    }
    if (t128 == 0) TS(wg ? 16 : 6);
    {
      float z[2][16];
#pragma unroll
      for (int j = -1; j <= 5; j++) {
        if (j >= 1) {
          const float* a = &acc[16 * (j - 1)];
          const float* tt = z[(j - 1) & 1];
#pragma unroll
          for (int h = 0; h < 16; h += 8)
            stmatrix4t(ad + (2 * (j - 1) + (h >> 3)) * 2048, and_or(pack_bf16(fmaf(a[h], tt[h], a[h]), fmaf(a[h + 1], tt[h + 1], a[h + 1])), uam, uom),
                       pack_bf16(fmaf(a[h + 2], tt[h + 2], a[h + 2]), fmaf(a[h + 3], tt[h + 3], a[h + 3])),
                       and_or(pack_bf16(fmaf(a[h + 4], tt[h + 4], a[h + 4]), fmaf(a[h + 5], tt[h + 5], a[h + 5])), uam, uom),
                       pack_bf16(fmaf(a[h + 6], tt[h + 6], a[h + 6]), fmaf(a[h + 7], tt[h + 7], a[h + 7])));
        }
        if (j >= 0 && j < 5) {
#pragma unroll
          for (int e = 0; e < 16; e++) asm("tanh.approx.f32 %0, %0;" : "+f"(z[j & 1][e]));
        }
        if (j < 4) {
#pragma unroll
          for (int e = 0; e < 16; e++) z[(j + 1) & 1][e] = gelu_arg(acc[16 * (j + 1) + e]);
        }
        if (j == 3 || j == 5) { fence_async_smem(); asm volatile("bar.arrive %0, 160;" ::"r"((j == 3 ? 11 : 13) + wgu) : "memory"); }
        if (j < 5) {
          if (j >= 0) reg_fence(z[j & 1]);
          if (j < 4) reg_fence(z[(j + 1) & 1]);
          if (__builtin_expect(wp == 0x7ffffff0 + j, 0)) __trap();
          reg_fence(acc);
        }
      }
      if (t128 == 0) TS(wg ? 29 : 28);
    }
    if (g2) {
      const int mb = wgu ^ r;
      uint32_t gb[18];
      {
        float a0 = 0.f, a1 = 0.f;
        if (wgu) {
          a0 = __bfloat162float(p.b2[s2 + 64 * mb + 16 * w + g]); a1 = __bfloat162float(p.b2[s2 + 64 * mb + 16 * w + 8 + g]);
          int it = 0;
          uint32_t bad;
          do {
            bad = 0;
#pragma unroll
            for (int i = 0; i < 18; i++) {
              const uint2 v = ld_rlx2(sc->mod + 3 * D_ + d2 + 8 * i + 2 * t);
              bad |= (v.x ^ tag16) | (v.y ^ tag16);
              gb[i] = __byte_perm(v.x, v.y, 0x7632);
            }
          } while (any(bad & 0xffffu) && ++it < SPIN_MAX);
        }
#pragma unroll
        for (int i = 0; i < 72; i++) acc[i] = (i & 2) ? a1 : a0;
      }
      rg.st++;
      gemm_main<3>(acc, sb4 + mb * 512 + LA, 0, sb4 + 1024 + (1 << 16), 0, wgu, rg, x1p, xr);
      if (t128 == 0) TS(wg ? 20 : 19);
      const uint32_t sx = sbase + XST * STAGE;
      if (wgu == 0) {
        uint4* dst = sc->part + z2 * 1152 + t128;
#pragma unroll
        for (int j = 0; j < 9; j++) {
          const float* a = &acc[8 * j];
          dst[j * 128] = make_uint4(set_tag(pack_bf16(a[0], a[1]), tag1), pack_bf16(a[2], a[3]), pack_bf16(a[4], a[5]), pack_bf16(a[6], a[7]));
        }
        if (tid == 0) TS(21);
        const uint4* src = sc->part + (z2 ^ 64) * 1152 + t128;
        uint4 v[9];
        uint32_t bad;
        int it = 0;
        do {
#pragma unroll
          for (int j = 0; j < 9; j++) v[j] = ld_rlx4(src + j * 128);
          bad = v[8].x ^ tag1;
#pragma unroll
          for (int j = 0; j < 8; j += 2) bad |= diff2(v[j].x, v[j + 1].x, tag1);
        } while (any(bad & 1) && ++it < SPIN_MAX);
#pragma unroll
        for (int j = 0; j < 9; j++) sts4(sx + t128 * 16 + j * 2048, v[j].x, v[j].y, v[j].z, v[j].w);
        bar_arrive(2 + w, 64);
        if (w == 0) {
#pragma unroll 1
          for (int i = 0; i < 3; i++) {
            bar_sync(11 + i, 160);
            if (elect()) tma_st2d(&maps.out, sx + 18432 + i * 6144, d2 + 48 * i, s2 + 64 * (r ^ 1));
            __syncwarp();
          }
          if (elect()) { bulk_commit_wait_read(); TS(22); }
          __syncwarp();
        }
      } else {
        mbar_wait(full0 + 8 * XST, rg.ph);
        bar_sync(2 + w, 64);
        if (t128 == 0) TS(5);
        if (tid == 128 && cta == 0) sc->cnt[C_EP] = ep;
        const uint32_t xa = sx + 18432 + (16 * w + (l & 15)) * 96 + (l >> 4) * 16;
#pragma unroll
        for (int c = 0; c < 3; c++) {
          uint32_t pv[3][4], xv[3][4];
#pragma unroll
          for (int j = 0; j < 3; j++) {
            asm volatile("ld.shared.v4.b32 {%0,%1,%2,%3}, [%4];" : "=r"(pv[j][0]), "=r"(pv[j][1]), "=r"(pv[j][2]), "=r"(pv[j][3]) : "r"(sx + t128 * 16 + (3 * c + j) * 2048) : "memory");
            asm volatile("ldmatrix.sync.aligned.m8n8.x4.shared.b16 {%0,%1,%2,%3}, [%4];" : "=r"(xv[j][0]), "=r"(xv[j][1]), "=r"(xv[j][2]), "=r"(xv[j][3]) : "r"(xa + c * 6144 + j * 32) : "memory");
          }
#pragma unroll
          for (int j = 0; j < 3; j++) {
            const float* a = &acc[8 * (3 * c + j)];
            uint32_t o[4];
#pragma unroll
            for (int e = 0; e < 4; e++)
              o[e] = hadd2(xv[j][e], hmul2(gb[2 * (3 * c + j) + (e >> 1)], pack_bf16(a[2 * e] + bf_lo(pv[j][e]), a[2 * e + 1] + bf_hi(pv[j][e]))));
            stmatrix4(xa + c * 6144 + j * 32, o[0], o[1], o[2], o[3]);
          }
          fence_async_smem();
          asm volatile("bar.arrive %0, 160;" ::"r"(11 + c) : "memory");
        }
        if (t128 == 0) TS(7);
        __syncwarp();
      }
    }
  }
}

typedef CUresult (*EncodeFn)(CUtensorMap*, CUtensorMapDataType, cuuint32_t, void*, const cuuint64_t*, const cuuint64_t*, const cuuint32_t*,
                             const cuuint32_t*, CUtensorMapInterleave, CUtensorMapSwizzle, CUtensorMapL2promotion, CUtensorMapFloatOOBfill);

struct Dim { cuuint64_t n, stride; cuuint32_t box; };
template <int RANK>
void make_map(EncodeFn enc, CUtensorMap* m, bool words, int swz, const void* ptr, const Dim (&d)[RANK]) {
  cuuint64_t gd[RANK], gs[RANK];
  cuuint32_t bx[RANK], es[RANK];
  for (int i = 0; i < RANK; i++) { gd[i] = d[i].n; gs[i] = d[i].stride; bx[i] = d[i].box; es[i] = 1; }
  enc(m, words ? CU_TENSOR_MAP_DATA_TYPE_UINT32 : CU_TENSOR_MAP_DATA_TYPE_BFLOAT16, RANK, const_cast<void*>(ptr), gd, gs + 1, bx, es,
      CU_TENSOR_MAP_INTERLEAVE_NONE, static_cast<CUtensorMapSwizzle>(swz),
      swz == 3 ? CU_TENSOR_MAP_L2_PROMOTION_L2_256B : CU_TENSOR_MAP_L2_PROMOTION_NONE, CU_TENSOR_MAP_FLOAT_OOB_FILL_NONE);
}

}

extern "C" void kernel_launch(void* const* d_in, const int* in_sizes, int n_in, void* d_out, int out_size) {
  (void)in_sizes; (void)n_in; (void)out_size;
  static EncodeFn enc = nullptr;
  static void *sptr = nullptr, *tptr = nullptr;
  if (!enc) {
    void* f = nullptr; cudaDriverEntryPointQueryResult qr;
    cudaGetDriverEntryPoint("cuTensorMapEncodeTiled", &f, cudaEnableDefault, &qr);
    enc = reinterpret_cast<EncodeFn>(f);
    cudaFuncSetAttribute(fused_kernel, cudaFuncAttributeMaxDynamicSharedMemorySize, SMEM_BYTES);
    cudaGetSymbolAddress(&sptr, g_s);
    cudaGetSymbolAddress(&tptr, T_TAB);
  }
  Params p;
  p.x = (const __nv_bfloat16*)d_in[0]; p.wr = (const __nv_bfloat16*)d_in[1]; p.wi = (const __nv_bfloat16*)d_in[2];
  p.b1 = (const __nv_bfloat16*)d_in[5]; p.b2 = (const __nv_bfloat16*)d_in[7];
  p.c = (const __nv_bfloat16*)d_in[8]; p.wmod = (const __nv_bfloat16*)d_in[9];
  p.w1 = (const __nv_bfloat16*)d_in[4]; p.w2 = (const __nv_bfloat16*)d_in[6];
  p.s = static_cast<Scratch*>(sptr); p.tab = static_cast<const uint4*>(tptr);
  Maps maps;
  make_map<4>(enc, &maps.w1a, false, 3, p.w1, {{64, 0, 64}, {16, 128 * 2 * F_, 4}, {128, 2 * F_, 16}, {72, 128, 2}});
  make_map<4>(enc, &maps.w1b, false, 3, p.w1, {{64, 0, 64}, {16, 128 * 2 * F_, 4}, {128, 2 * F_, 16}, {72, 128, 3}});
  make_map<3>(enc, &maps.w2, false, 3, p.w2, {{64, 0, 64}, {F_, 2 * S_, 64}, {32, 128, 2}});
  make_map<2>(enc, &maps.x1, false, 0, p.s->x1, {{D_, 0, 48}, {S_, 2 * D_, 64}});
  make_map<2>(enc, &maps.out, false, 0, d_out, {{D_, 0, 48}, {S_, 2 * D_, 64}});
  make_map<2>(enc, &maps.z1, true, 0, p.s->z1, {{5120, 0, 40}, {120, 20480, 60}});
  for (int i = 0; i < 2; i++) make_map<2>(enc, &maps.z2[i], true, 0, p.s->z2, {{4800, 0, i ? 16u : 24u}, {128, 19200, 128}});
  for (int i = 0; i < 4; i++) make_map<2>(enc, &maps.wf[i], false, 2 - (i & 1), (i & 2) ? p.wi : p.wr, {{16 * DF_, 0, (i & 1) ? 16u : 32u}, {128, 32 * DF_, 128}});
  make_map<2>(enc, &maps.wm, false, 1, p.wmod, {{6 * D_, 0, 16}, {D_, 12 * D_, 192}});
  for (int i = 0; i < 2; i++) make_map<3>(enc, &maps.h3[i], true, 0, p.s->h3, {{1024, 0, 64}, {144, 4096, 18}, {4, 144 * 4096, i ? 4u - H3G : H3G}});
  fused_kernel<<<NCTA, NTHR, SMEM_BYTES, cudaStreamPerThread>>>(p, maps);
}
```

```cpp
#include <cuda_runtime.h>
#include <cuda_bf16.h>
#include <cuda.h>
#include <stdint.h>

namespace {

constexpr int S_ = 2048, D_ = 576, DF_ = 289, F_ = 4608;
constexpr int NCTA = 132, NTHR = 384;
constexpr int STAGE = 36864, NST = 6;
constexpr uint32_t sbase = 1024, full0 = sbase + NST * STAGE, empty0 = full0 + 8 * NST, red = full0 + 256;
constexpr int SMEM_BYTES = NST * STAGE + 256 + 512 + 4 * D_ + 512;
constexpr int O_NRM = 0, O_B1 = 19456, O_Z1 = 38912, O_P2 = 59392, O_ST = 3 * STAGE;
constexpr int O_RAW = 4 * STAGE;
constexpr int O_IN = 4 * STAGE, O_Y = O_IN + 19456, O_B3 = O_IN + 38912, O_MOD = O_IN + 57344;

__device__ __align__(128) const uint32_t T_TAB[5632] = {
0x3f803f80,0xbf803f80,0x3f803f80,0xbf803f80,0x3f803f80,0xbf803f80,0x3f803f80,0xbf803f80,0x3f803f80,0xbf803f80,0x3f803f80,0xbf803f80,
0x3f803f80,0xbf803f80,0x3f803f80,0xbf803f80,0x3f7f3f80,0xbdc90000,0x3f223f35,0xbf46bf35,0x3f753f7b,0xbe95be48,0x3ef13f0e,0xbf62bf55,
0x3f623f6d,0xbef1bec4,0x3e953ec4,0xbf75bf6d,0x3f463f55,0xbf22bf0e,0x3dc93e48,0xbf7fbf7b,0x3f7b3f80,0xbe480000,0xbe480000,0xbf7bbf80,
0x3f553f6d,0xbf0ebec4,0xbf0ebec4,0xbf55bf6d,0x3f0e3f35,0xbf55bf35,0xbf55bf35,0xbf0ebf35,0x3e483ec4,0xbf7bbf6d,0xbf7bbf6d,0xbe48bec4,
0x3f753f80,0xbe950000,0xbf62bf35,0xbef1bf35,0x3f223f55,0xbf46bf0e,0xbf7fbf7b,0x3dc9be48,0x3dc93ec4,0xbf7fbf6d,0xbf46bf6d,0x3f223ec4,
0xbef1be48,0xbf62bf7b,0xbe95bf0e,0x3f753f55,0x3f6d3f80,0xbec40000,0xbf6dbf80,0x3ec40000,0x3ec43f35,0xbf6dbf35,0xbec4bf35,0x3f6d3f35,
0xbec40000,0xbf6dbf80,0x3ec40000,0x3f6d3f80,0xbf6dbf35,0xbec4bf35,0x3f6d3f35,0x3ec43f35,0x3f623f80,0xbef10000,0xbe95bf35,0x3f753f35,
0x3dc93f0e,0xbf7fbf55,0x3f223e48,0x3f463f7b,0xbf46bec4,0xbf22bf6d,0x3f7f3f6d,0xbdc93ec4,0xbf75bf7b,0x3e95be48,0x3ef13f55,0xbf62bf0e,
0x3f553f80,0xbf0e0000,0x3f0e0000,0x3f553f80,0xbe483ec4,0xbf7bbf6d,0x3f7b3f6d,0xbe483ec4,0xbf7bbf35,0xbe48bf35,0x3e483f35,0xbf7bbf35,
0xbf0ebf6d,0x3f553ec4,0xbf55bec4,0xbf0ebf6d,0x3f463f80,0xbf220000,0x3f7f3f35,0x3dc93f35,0xbef13e48,0xbf62bf7b,0x3e953f55,0xbf75bf0e,
0xbf75bf6d,0x3e95bec4,0xbf62bec4,0xbef1bf6d,0x3dc9bf0e,0x3f7f3f55,0xbf22bf7b,0x3f463e48,0x3f353f80,0xbf350000,0x3f353f80,0xbf350000,
0xbf350000,0xbf35bf80,0xbf350000,0xbf35bf80,0xbf35bf80,0x3f350000,0xbf35bf80,0x3f350000,0x3f350000,0x3f353f80,0x3f350000,0x3f353f80,
0x3f223f80,0xbf460000,0xbdc93f35,0xbf7fbf35,0xbf62be48,0xbef1bf7b,0xbf75bf55,0x3e95bf0e,0xbe95bf6d,0x3f753ec4,0x3ef1bec4,0x3f623f6d,
0x3f7f3f0e,0x3dc93f55,0x3f463f7b,0xbf223e48,0x3f0e3f80,0xbf550000,0xbf550000,0xbf0ebf80,0xbf7bbec4,0xbe48bf6d,0xbe48bf6d,0x3f7b3ec4,
0x3e48bf35,0x3f7b3f35,0x3f7b3f35,0xbe483f35,0x3f553f6d,0xbf0e3ec4,0xbf0e3ec4,0xbf55bf6d,0x3ef13f80,0xbf620000,0xbf75bf35,0x3e95bf35,
0xbf7fbf0e,0x3dc9bf55,0x3f46be48,0x3f223f7b,0x3f22bec4,0x3f463f6d,0x3dc93f6d,0xbf7fbec4,0x3e953f7b,0xbf75be48,0xbf62bf55,0x3ef1bf0e,
0x3ec43f80,0xbf6d0000,0xbec4bf80,0x3f6d0000,0xbf6dbf35,0x3ec4bf35,0x3f6d3f35,0xbec43f35,0x3f6d0000,0x3ec43f80,0xbf6d0000,0xbec4bf80,
0xbec43f35,0xbf6dbf35,0x3ec4bf35,0x3f6d3f35,0x3e953f80,0xbf750000,0x3ef1bf35,0x3f623f35,0xbf46bf55,0x3f22bf0e,0x3dc93f7b,0xbf7fbe48,
0x3f7f3ec4,0xbdc93f6d,0xbf22bf6d,0x3f46bec4,0xbf623e48,0xbef1bf7b,0x3f753f0e,0xbe953f55,0x3e483f80,0xbf7b0000,0x3f7b0000,0x3e483f80,
0xbf0ebf6d,0x3f55bec4,0xbf553ec4,0xbf0ebf6d,0x3f553f35,0xbf0e3f35,0x3f0ebf35,0x3f553f35,0xbf7bbec4,0x3e48bf6d,0xbe483f6d,0xbf7bbec4,
0x3dc93f80,0xbf7f0000,0x3f463f35,0xbf223f35,0xbe95bf7b,0x3f75be48,0xbf62bf0e,0x3ef1bf55,0x3ef13f6d,0xbf623ec4,0x3f753ec4,0xbe953f6d,
0xbf22bf55,0x3f46bf0e,0xbf7fbe48,0x3dc9bf7b,0x3f80,0xbf800000,0x3f80,0xbf800000,0xbf80,0x3f800000,0xbf80,0x3f800000,
0x3f80,0xbf800000,0x3f80,0xbf800000,0xbf80,0x3f800000,0xbf80,0x3f800000,0xbdc93f80,0xbf7f0000,0xbf463f35,0xbf22bf35,
0x3e95bf7b,0x3f753e48,0x3f62bf0e,0x3ef13f55,0xbef13f6d,0xbf62bec4,0xbf753ec4,0xbe95bf6d,0x3f22bf55,0x3f463f0e,0x3f7fbe48,0x3dc93f7b,
0xbe483f80,0xbf7b0000,0xbf7b0000,0x3e48bf80,0x3f0ebf6d,0x3f553ec4,0x3f553ec4,0xbf0e3f6d,0xbf553f35,0xbf0ebf35,0xbf0ebf35,0x3f55bf35,
0x3f7bbec4,0x3e483f6d,0x3e483f6d,0xbf7b3ec4,0xbe953f80,0xbf750000,0xbef1bf35,0x3f62bf35,0x3f46bf55,0x3f223f0e,0xbdc93f7b,0xbf7f3e48,
0xbf7f3ec4,0xbdc9bf6d,0x3f22bf6d,0x3f463ec4,0x3f623e48,0xbef13f7b,0xbf753f0e,0xbe95bf55,0xbec43f80,0xbf6d0000,0x3ec4bf80,0x3f6d0000,
0x3f6dbf35,0x3ec43f35,0xbf6d3f35,0xbec4bf35,0xbf6d0000,0x3ec4bf80,0x3f6d0000,0xbec43f80,0x3ec43f35,0xbf6d3f35,0xbec4bf35,0x3f6dbf35,
0xbef13f80,0xbf620000,0x3f75bf35,0x3e953f35,0x3f7fbf0e,0x3dc93f55,0xbf46be48,0x3f22bf7b,0xbf22bec4,0x3f46bf6d,0xbdc93f6d,0xbf7f3ec4,
0xbe953f7b,0xbf753e48,0x3f62bf55,0x3ef13f0e,0xbf0e3f80,0xbf550000,0x3f550000,0xbf0e3f80,0x3f7bbec4,0xbe483f6d,0x3e48bf6d,0x3f7bbec4,
0xbe48bf35,0x3f7bbf35,0xbf7b3f35,0xbe48bf35,0xbf553f6d,0xbf0ebec4,0x3f0e3ec4,0xbf553f6d,0xbf223f80,0xbf460000,0x3dc93f35,0xbf7f3f35,
0x3f62be48,0xbef13f7b,0x3f75bf55,0x3e953f0e,0x3e95bf6d,0x3f75bec4,0xbef1bec4,0x3f62bf6d,0xbf7f3f0e,0x3dc9bf55,0xbf463f7b,0xbf22be48,
0xbf353f80,0xbf350000,0xbf353f80,0xbf350000,0x3f350000,0xbf353f80,0x3f350000,0xbf353f80,0x3f35bf80,0x3f350000,0x3f35bf80,0x3f350000,
0xbf350000,0x3f35bf80,0xbf350000,0x3f35bf80,0xbf463f80,0xbf220000,0xbf7f3f35,0x3dc9bf35,0x3ef13e48,0xbf623f7b,0xbe953f55,0xbf753f0e,
0x3f75bf6d,0x3e953ec4,0x3f62bec4,0xbef13f6d,0xbdc9bf0e,0x3f7fbf55,0x3f22bf7b,0x3f46be48,0xbf553f80,0xbf0e0000,0xbf0e0000,0x3f55bf80,
0x3e483ec4,0xbf7b3f6d,0xbf7b3f6d,0xbe48bec4,0x3f7bbf35,0xbe483f35,0xbe483f35,0xbf7b3f35,0x3f0ebf6d,0x3f55bec4,0x3f55bec4,0xbf0e3f6d,
0xbf623f80,0xbef10000,0x3e95bf35,0x3f75bf35,0xbdc93f0e,0xbf7f3f55,0xbf223e48,0x3f46bf7b,0x3f46bec4,0xbf223f6d,0xbf7f3f6d,0xbdc9bec4,
0x3f75bf7b,0x3e953e48,0xbef13f55,0xbf623f0e,0xbf6d3f80,0xbec40000,0x3f6dbf80,0x3ec40000,0xbec43f35,0xbf6d3f35,0x3ec4bf35,0x3f6dbf35,
0x3ec40000,0xbf6d3f80,0xbec40000,0x3f6dbf80,0x3f6dbf35,0xbec43f35,0xbf6d3f35,0x3ec4bf35,0xbf753f80,0xbe950000,0x3f62bf35,0xbef13f35,
0xbf223f55,0xbf463f0e,0x3f7fbf7b,0x3dc93e48,0xbdc93ec4,0xbf7f3f6d,0x3f46bf6d,0x3f22bec4,0x3ef1be48,0xbf623f7b,0x3e95bf0e,0x3f75bf55,
0xbf7b3f80,0xbe480000,0x3e480000,0xbf7b3f80,0xbf553f6d,0xbf0e3ec4,0x3f0ebec4,0xbf553f6d,0xbf0e3f35,0xbf553f35,0x3f55bf35,0xbf0e3f35,
0xbe483ec4,0xbf7b3f6d,0x3f7bbf6d,0xbe483ec4,0xbf7f3f80,0xbdc90000,0xbf223f35,0xbf463f35,0xbf753f7b,0xbe953e48,0xbef13f0e,0xbf623f55,
0xbf623f6d,0xbef13ec4,0xbe953ec4,0xbf753f6d,0xbf463f55,0xbf223f0e,0xbdc93e48,0xbf7f3f7b,0x3f803f80,0xbf803f80,0x3f803f80,0xbf803f80,
0x3f803f80,0xbf803f80,0x3f803f80,0xbf803f80,0x3f803f80,0xbf803f80,0x3f803f80,0xbf803f80,0x3f803f80,0xbf803f80,0x3f803f80,0xbf803f80,
0xbdc90000,0xbf7fbf80,0xbf46bf35,0xbf22bf35,0xbe95be48,0xbf75bf7b,0xbf62bf55,0xbef1bf0e,0xbef1bec4,0xbf62bf6d,0xbf75bf6d,0xbe95bec4,
0xbf22bf0e,0xbf46bf55,0xbf7fbf7b,0xbdc9be48,0xbf7bbf80,0x3e480000,0x3e480000,0x3f7b3f80,0xbf55bf6d,0x3f0e3ec4,0x3f0e3ec4,0x3f553f6d,
0xbf0ebf35,0x3f553f35,0x3f553f35,0x3f0e3f35,0xbe48bec4,0x3f7b3f6d,0x3f7b3f6d,0x3e483ec4,0x3e950000,0x3f753f80,0x3ef13f35,0xbf62bf35,
0x3f463f0e,0x3f223f55,0xbdc93e48,0xbf7fbf7b,0x3f7f3f6d,0x3dc93ec4,0xbf22bec4,0xbf46bf6d,0x3f623f7b,0xbef1be48,0xbf75bf55,0xbe95bf0e,
0x3f6d3f80,0xbec40000,0xbf6dbf80,0x3ec40000,0x3ec43f35,0xbf6dbf35,0xbec4bf35,0x3f6d3f35,0xbec40000,0xbf6dbf80,0x3ec40000,0x3f6d3f80,
0xbf6dbf35,0xbec4bf35,0x3f6d3f35,0x3ec43f35,0xbef10000,0xbf62bf80,0x3f753f35,0x3e953f35,0xbf7fbf55,0xbdc9bf0e,0x3f463f7b,0xbf22be48,
0xbf22bf6d,0x3f463ec4,0xbdc93ec4,0xbf7fbf6d,0x3e95be48,0x3f753f7b,0xbf62bf0e,0xbef1bf55,0xbf55bf80,0x3f0e0000,0xbf0e0000,0xbf55bf80,
0x3e48bec4,0x3f7b3f6d,0xbf7bbf6d,0x3e48bec4,0x3f7b3f35,0x3e483f35,0xbe48bf35,0x3f7b3f35,0x3f0e3f6d,0xbf55bec4,0x3f553ec4,0x3f0e3f6d,
0x3f220000,0x3f463f80,0xbdc9bf35,0x3f7f3f35,0x3f623f7b,0xbef13e48,0x3f753f0e,0x3e953f55,0xbe953ec4,0xbf75bf6d,0x3ef13f6d,0xbf62bec4,
0xbf7fbf55,0x3dc9bf0e,0xbf46be48,0xbf22bf7b,0x3f353f80,0xbf350000,0x3f353f80,0xbf350000,0xbf350000,0xbf35bf80,0xbf350000,0xbf35bf80,
0xbf35bf80,0x3f350000,0xbf35bf80,0x3f350000,0x3f350000,0x3f353f80,0x3f350000,0x3f353f80,0xbf460000,0xbf22bf80,0xbf7fbf35,0x3dc9bf35,
0xbef1bf7b,0x3f623e48,0x3e95bf0e,0x3f753f55,0x3f753ec4,0x3e953f6d,0x3f623f6d,0xbef13ec4,0x3dc93f55,0xbf7fbf0e,0xbf223e48,0xbf46bf7b,
0xbf0ebf80,0x3f550000,0x3f550000,0x3f0e3f80,0x3f7b3ec4,0x3e483f6d,0x3e483f6d,0xbf7bbec4,0xbe483f35,0xbf7bbf35,0xbf7bbf35,0x3e48bf35,
0xbf55bf6d,0x3f0ebec4,0x3f0ebec4,0x3f553f6d,0x3f620000,0x3ef13f80,0xbe953f35,0xbf75bf35,0xbdc93f55,0xbf7fbf0e,0xbf22bf7b,0x3f46be48,
0xbf46bf6d,0x3f22bec4,0x3f7f3ec4,0x3dc93f6d,0x3f753e48,0x3e953f7b,0xbef13f0e,0xbf62bf55,0x3ec43f80,0xbf6d0000,0xbec4bf80,0x3f6d0000,
0xbf6dbf35,0x3ec4bf35,0x3f6d3f35,0xbec43f35,0x3f6d0000,0x3ec43f80,0xbf6d0000,0xbec4bf80,0xbec43f35,0xbf6dbf35,0x3ec4bf35,0x3f6d3f35,
0xbf750000,0xbe95bf80,0x3f623f35,0xbef13f35,0x3f22bf0e,0x3f463f55,0xbf7fbe48,0xbdc9bf7b,0xbdc93f6d,0xbf7fbec4,0x3f46bec4,0x3f223f6d,
0xbef1bf7b,0x3f62be48,0xbe953f55,0xbf75bf0e,0xbe48bf80,0x3f7b0000,0xbf7b0000,0xbe48bf80,0x3f0e3f6d,0xbf553ec4,0x3f55bec4,0x3f0e3f6d,
0xbf55bf35,0x3f0ebf35,0xbf0e3f35,0xbf55bf35,0x3f7b3ec4,0xbe483f6d,0x3e48bf6d,0x3f7b3ec4,0x3f7f0000,0x3dc93f80,0x3f22bf35,0x3f463f35,
0xbf753e48,0xbe95bf7b,0xbef13f55,0xbf62bf0e,0x3f62bec4,0x3ef13f6d,0x3e95bf6d,0x3f753ec4,0xbf463f0e,0xbf22bf55,0xbdc93f7b,0xbf7fbe48,
0x3f80,0xbf800000,0x3f80,0xbf800000,0xbf80,0x3f800000,0xbf80,0x3f800000,0x3f80,0xbf800000,0x3f80,0xbf800000,
0xbf80,0x3f800000,0xbf80,0x3f800000,0xbf7f0000,0x3dc9bf80,0xbf22bf35,0x3f46bf35,0x3f753e48,0xbe953f7b,0x3ef13f55,0xbf623f0e,
0xbf62bec4,0x3ef1bf6d,0xbe95bf6d,0x3f75bec4,0x3f463f0e,0xbf223f55,0x3dc93f7b,0xbf7f3e48,0x3e48bf80,0x3f7b0000,0x3f7b0000,0xbe483f80,
0xbf0e3f6d,0xbf55bec4,0xbf55bec4,0x3f0ebf6d,0x3f55bf35,0x3f0e3f35,0x3f0e3f35,0xbf553f35,0xbf7b3ec4,0xbe48bf6d,0xbe48bf6d,0x3f7bbec4,
0x3f750000,0xbe953f80,0xbf623f35,0xbef1bf35,0xbf22bf0e,0x3f46bf55,0x3f7fbe48,0xbdc93f7b,0x3dc93f6d,0xbf7f3ec4,0xbf46bec4,0x3f22bf6d,
0x3ef1bf7b,0x3f623e48,0x3e953f55,0xbf753f0e,0xbec43f80,0xbf6d0000,0x3ec4bf80,0x3f6d0000,0x3f6dbf35,0x3ec43f35,0xbf6d3f35,0xbec4bf35,
0xbf6d0000,0x3ec4bf80,0x3f6d0000,0xbec43f80,0x3ec43f35,0xbf6d3f35,0xbec4bf35,0x3f6dbf35,0xbf620000,0x3ef1bf80,0x3e953f35,0xbf753f35,
0x3dc93f55,0xbf7f3f0e,0x3f22bf7b,0x3f463e48,0x3f46bf6d,0x3f223ec4,0xbf7f3ec4,0x3dc9bf6d,0xbf753e48,0x3e95bf7b,0x3ef13f0e,0xbf623f55,
0x3f0ebf80,0x3f550000,0xbf550000,0x3f0ebf80,0xbf7b3ec4,0x3e48bf6d,0xbe483f6d,0xbf7b3ec4,0x3e483f35,0xbf7b3f35,0x3f7bbf35,0x3e483f35,
0x3f55bf6d,0x3f0e3ec4,0xbf0ebec4,0x3f55bf6d,0x3f460000,0xbf223f80,0x3f7fbf35,0x3dc93f35,0x3ef1bf7b,0x3f62be48,0xbe95bf0e,0x3f75bf55,
0xbf753ec4,0x3e95bf6d,0xbf623f6d,0xbef1bec4,0xbdc93f55,0xbf7f3f0e,0x3f223e48,0xbf463f7b,0xbf353f80,0xbf350000,0xbf353f80,0xbf350000,
0x3f350000,0xbf353f80,0x3f350000,0xbf353f80,0x3f35bf80,0x3f350000,0x3f35bf80,0x3f350000,0xbf350000,0x3f35bf80,0xbf350000,0x3f35bf80,
0xbf220000,0x3f46bf80,0x3dc9bf35,0x3f7fbf35,0xbf623f7b,0xbef1be48,0xbf753f0e,0x3e95bf55,0x3e953ec4,0xbf753f6d,0xbef13f6d,0xbf623ec4,
0x3f7fbf55,0x3dc93f0e,0x3f46be48,0xbf223f7b,0x3f55bf80,0x3f0e0000,0x3f0e0000,0xbf553f80,0xbe48bec4,0x3f7bbf6d,0x3f7bbf6d,0x3e483ec4,
0xbf7b3f35,0x3e48bf35,0x3e48bf35,0x3f7bbf35,0xbf0e3f6d,0xbf553ec4,0xbf553ec4,0x3f0ebf6d,0x3ef10000,0xbf623f80,0xbf753f35,0x3e95bf35,
0x3f7fbf55,0xbdc93f0e,0xbf463f7b,0xbf223e48,0x3f22bf6d,0x3f46bec4,0x3dc93ec4,0xbf7f3f6d,0xbe95be48,0x3f75bf7b,0x3f62bf0e,0xbef13f55,
0xbf6d3f80,0xbec40000,0x3f6dbf80,0x3ec40000,0xbec43f35,0xbf6d3f35,0x3ec4bf35,0x3f6dbf35,0x3ec40000,0xbf6d3f80,0xbec40000,0x3f6dbf80,
0x3f6dbf35,0xbec43f35,0xbf6d3f35,0x3ec4bf35,0xbe950000,0x3f75bf80,0xbef13f35,0xbf623f35,0xbf463f0e,0x3f22bf55,0x3dc93e48,0xbf7f3f7b,
0xbf7f3f6d,0x3dc9bec4,0x3f22bec4,0xbf463f6d,0xbf623f7b,0xbef13e48,0x3f75bf55,0xbe953f0e,0x3f7bbf80,0x3e480000,0xbe480000,0x3f7bbf80,
0x3f55bf6d,0x3f0ebec4,0xbf0e3ec4,0x3f55bf6d,0x3f0ebf35,0x3f55bf35,0xbf553f35,0x3f0ebf35,0x3e48bec4,0x3f7bbf6d,0xbf7b3f6d,0x3e48bec4,
0x3dc90000,0xbf7f3f80,0x3f46bf35,0xbf223f35,0x3e95be48,0xbf753f7b,0x3f62bf55,0xbef13f0e,0x3ef1bec4,0xbf623f6d,0x3f75bf6d,0xbe953ec4,
0x3f22bf0e,0xbf463f55,0x3f7fbf7b,0xbdc93e48,0x3f803f80,0xbf803f80,0x3f803f80,0xbf803f80,0x3f803f80,0xbf803f80,0x3f803f80,0xbf803f80,
0x3f803f80,0xbf803f80,0x3f803f80,0xbf803f80,0x3f803f80,0xbf803f80,0x3f803f80,0xbf803f80,0xbf7fbf80,0x3dc90000,0xbf22bf35,0x3f463f35,
0xbf75bf7b,0x3e953e48,0xbef1bf0e,0x3f623f55,0xbf62bf6d,0x3ef13ec4,0xbe95bec4,0x3f753f6d,0xbf46bf55,0x3f223f0e,0xbdc9be48,0x3f7f3f7b,
0x3f7b3f80,0xbe480000,0xbe480000,0xbf7bbf80,0x3f553f6d,0xbf0ebec4,0xbf0ebec4,0xbf55bf6d,0x3f0e3f35,0xbf55bf35,0xbf55bf35,0xbf0ebf35,
0x3e483ec4,0xbf7bbf6d,0xbf7bbf6d,0xbe48bec4,0xbf75bf80,0x3e950000,0x3f623f35,0x3ef13f35,0xbf22bf55,0x3f463f0e,0x3f7f3f7b,0xbdc93e48,
0xbdc9bec4,0x3f7f3f6d,0x3f463f6d,0xbf22bec4,0x3ef13e48,0x3f623f7b,0x3e953f0e,0xbf75bf55,0x3f6d3f80,0xbec40000,0xbf6dbf80,0x3ec40000,
0x3ec43f35,0xbf6dbf35,0xbec4bf35,0x3f6d3f35,0xbec40000,0xbf6dbf80,0x3ec40000,0x3f6d3f80,0xbf6dbf35,0xbec4bf35,0x3f6d3f35,0x3ec43f35,
0xbf62bf80,0x3ef10000,0x3e953f35,0xbf75bf35,0xbdc9bf0e,0x3f7f3f55,0xbf22be48,0xbf46bf7b,0x3f463ec4,0x3f223f6d,0xbf7fbf6d,0x3dc9bec4,
0x3f753f7b,0xbe953e48,0xbef1bf55,0x3f623f0e,0x3f553f80,0xbf0e0000,0x3f0e0000,0x3f553f80,0xbe483ec4,0xbf7bbf6d,0x3f7b3f6d,0xbe483ec4,
0xbf7bbf35,0xbe48bf35,0x3e483f35,0xbf7bbf35,0xbf0ebf6d,0x3f553ec4,0xbf55bec4,0xbf0ebf6d,0xbf46bf80,0x3f220000,0xbf7fbf35,0xbdc9bf35,
0x3ef1be48,0x3f623f7b,0xbe95bf55,0x3f753f0e,0x3f753f6d,0xbe953ec4,0x3f623ec4,0x3ef13f6d,0xbdc93f0e,0xbf7fbf55,0x3f223f7b,0xbf46be48,
0x3f353f80,0xbf350000,0x3f353f80,0xbf350000,0xbf350000,0xbf35bf80,0xbf350000,0xbf35bf80,0xbf35bf80,0x3f350000,0xbf35bf80,0x3f350000,
0x3f350000,0x3f353f80,0x3f350000,0x3f353f80,0xbf22bf80,0x3f460000,0x3dc9bf35,0x3f7f3f35,0x3f623e48,0x3ef13f7b,0x3f753f55,0xbe953f0e,
0x3e953f6d,0xbf75bec4,0xbef13ec4,0xbf62bf6d,0xbf7fbf0e,0xbdc9bf55,0xbf46bf7b,0x3f22be48,0x3f0e3f80,0xbf550000,0xbf550000,0xbf0ebf80,
0xbf7bbec4,0xbe48bf6d,0xbe48bf6d,0x3f7b3ec4,0x3e48bf35,0x3f7b3f35,0x3f7b3f35,0xbe483f35,0x3f553f6d,0xbf0e3ec4,0xbf0e3ec4,0xbf55bf6d,
0xbef1bf80,0x3f620000,0x3f753f35,0xbe953f35,0x3f7f3f0e,0xbdc93f55,0xbf463e48,0xbf22bf7b,0xbf223ec4,0xbf46bf6d,0xbdc9bf6d,0x3f7f3ec4,
0xbe95bf7b,0x3f753e48,0x3f623f55,0xbef13f0e,0x3ec43f80,0xbf6d0000,0xbec4bf80,0x3f6d0000,0xbf6dbf35,0x3ec4bf35,0x3f6d3f35,0xbec43f35,
0x3f6d0000,0x3ec43f80,0xbf6d0000,0xbec4bf80,0xbec43f35,0xbf6dbf35,0x3ec4bf35,0x3f6d3f35,0xbe95bf80,0x3f750000,0xbef13f35,0xbf62bf35,
0x3f463f55,0xbf223f0e,0xbdc9bf7b,0x3f7f3e48,0xbf7fbec4,0x3dc9bf6d,0x3f223f6d,0xbf463ec4,0x3f62be48,0x3ef13f7b,0xbf75bf0e,0x3e95bf55,
0x3e483f80,0xbf7b0000,0x3f7b0000,0x3e483f80,0xbf0ebf6d,0x3f55bec4,0xbf553ec4,0xbf0ebf6d,0x3f553f35,0xbf0e3f35,0x3f0ebf35,0x3f553f35,
0xbf7bbec4,0x3e48bf6d,0xbe483f6d,0xbf7bbec4,0xbdc9bf80,0x3f7f0000,0xbf46bf35,0x3f22bf35,0x3e953f7b,0xbf753e48,0x3f623f0e,0xbef13f55,
0xbef1bf6d,0x3f62bec4,0xbf75bec4,0x3e95bf6d,0x3f223f55,0xbf463f0e,0x3f7f3e48,0xbdc93f7b,0x3f80,0xbf800000,0x3f80,0xbf800000,
0xbf80,0x3f800000,0xbf80,0x3f800000,0x3f80,0xbf800000,0x3f80,0xbf800000,0xbf80,0x3f800000,0xbf80,0x3f800000,
0x3dc9bf80,0x3f7f0000,0x3f46bf35,0x3f223f35,0xbe953f7b,0xbf75be48,0xbf623f0e,0xbef1bf55,0x3ef1bf6d,0x3f623ec4,0x3f75bec4,0x3e953f6d,
0xbf223f55,0xbf46bf0e,0xbf7f3e48,0xbdc9bf7b,0xbe483f80,0xbf7b0000,0xbf7b0000,0x3e48bf80,0x3f0ebf6d,0x3f553ec4,0x3f553ec4,0xbf0e3f6d,
0xbf553f35,0xbf0ebf35,0xbf0ebf35,0x3f55bf35,0x3f7bbec4,0x3e483f6d,0x3e483f6d,0xbf7b3ec4,0x3e95bf80,0x3f750000,0x3ef13f35,0xbf623f35,
0xbf463f55,0xbf22bf0e,0x3dc9bf7b,0x3f7fbe48,0x3f7fbec4,0x3dc93f6d,0xbf223f6d,0xbf46bec4,0xbf62be48,0x3ef1bf7b,0x3f75bf0e,0x3e953f55,
0xbec43f80,0xbf6d0000,0x3ec4bf80,0x3f6d0000,0x3f6dbf35,0x3ec43f35,0xbf6d3f35,0xbec4bf35,0xbf6d0000,0x3ec4bf80,0x3f6d0000,0xbec43f80,
0x3ec43f35,0xbf6d3f35,0xbec4bf35,0x3f6dbf35,0x3ef1bf80,0x3f620000,0xbf753f35,0xbe95bf35,0xbf7f3f0e,0xbdc9bf55,0x3f463e48,0xbf223f7b,
0x3f223ec4,0xbf463f6d,0x3dc9bf6d,0x3f7fbec4,0x3e95bf7b,0x3f75be48,0xbf623f55,0xbef1bf0e,0xbf0e3f80,0xbf550000,0x3f550000,0xbf0e3f80,
0x3f7bbec4,0xbe483f6d,0x3e48bf6d,0x3f7bbec4,0xbe48bf35,0x3f7bbf35,0xbf7b3f35,0xbe48bf35,0xbf553f6d,0xbf0ebec4,0x3f0e3ec4,0xbf553f6d,
0x3f22bf80,0x3f460000,0xbdc9bf35,0x3f7fbf35,0xbf623e48,0x3ef1bf7b,0xbf753f55,0xbe95bf0e,0xbe953f6d,0xbf753ec4,0x3ef13ec4,0xbf623f6d,
0x3f7fbf0e,0xbdc93f55,0x3f46bf7b,0x3f223e48,0xbf353f80,0xbf350000,0xbf353f80,0xbf350000,0x3f350000,0xbf353f80,0x3f350000,0xbf353f80,
0x3f35bf80,0x3f350000,0x3f35bf80,0x3f350000,0xbf350000,0x3f35bf80,0xbf350000,0x3f35bf80,0x3f46bf80,0x3f220000,0x3f7fbf35,0xbdc93f35,
0xbef1be48,0x3f62bf7b,0x3e95bf55,0x3f75bf0e,0xbf753f6d,0xbe95bec4,0xbf623ec4,0x3ef1bf6d,0x3dc93f0e,0xbf7f3f55,0xbf223f7b,0xbf463e48,
0xbf553f80,0xbf0e0000,0xbf0e0000,0x3f55bf80,0x3e483ec4,0xbf7b3f6d,0xbf7b3f6d,0xbe48bec4,0x3f7bbf35,0xbe483f35,0xbe483f35,0xbf7b3f35,
0x3f0ebf6d,0x3f55bec4,0x3f55bec4,0xbf0e3f6d,0x3f62bf80,0x3ef10000,0xbe953f35,0xbf753f35,0x3dc9bf0e,0x3f7fbf55,0x3f22be48,0xbf463f7b,
0xbf463ec4,0x3f22bf6d,0x3f7fbf6d,0x3dc93ec4,0xbf753f7b,0xbe95be48,0x3ef1bf55,0x3f62bf0e,0xbf6d3f80,0xbec40000,0x3f6dbf80,0x3ec40000,
0xbec43f35,0xbf6d3f35,0x3ec4bf35,0x3f6dbf35,0x3ec40000,0xbf6d3f80,0xbec40000,0x3f6dbf80,0x3f6dbf35,0xbec43f35,0xbf6d3f35,0x3ec4bf35,
0x3f75bf80,0x3e950000,0xbf623f35,0x3ef1bf35,0x3f22bf55,0x3f46bf0e,0xbf7f3f7b,0xbdc9be48,0x3dc9bec4,0x3f7fbf6d,0xbf463f6d,0xbf223ec4,
0xbef13e48,0x3f62bf7b,0xbe953f0e,0xbf753f55,0xbf7b3f80,0xbe480000,0x3e480000,0xbf7b3f80,0xbf553f6d,0xbf0e3ec4,0x3f0ebec4,0xbf553f6d,
0xbf0e3f35,0xbf553f35,0x3f55bf35,0xbf0e3f35,0xbe483ec4,0xbf7b3f6d,0x3f7bbf6d,0xbe483ec4,0x3f7fbf80,0x3dc90000,0x3f22bf35,0x3f46bf35,
0x3f75bf7b,0x3e95be48,0x3ef1bf0e,0x3f62bf55,0x3f62bf6d,0x3ef1bec4,0x3e95bec4,0x3f75bf6d,0x3f46bf55,0x3f22bf0e,0x3dc9be48,0x3f7fbf7b,
0x3f803f80,0xbf803f80,0x3f803f80,0xbf803f80,0x3f803f80,0xbf803f80,0x3f803f80,0xbf803f80,0x3f803f80,0xbf803f80,0x3f803f80,0xbf803f80,
0x3f803f80,0xbf803f80,0x3f803f80,0xbf803f80,0x3dc90000,0x3f7f3f80,0x3f463f35,0x3f223f35,0x3e953e48,0x3f753f7b,0x3f623f55,0x3ef13f0e,
0x3ef13ec4,0x3f623f6d,0x3f753f6d,0x3e953ec4,0x3f223f0e,0x3f463f55,0x3f7f3f7b,0x3dc93e48,0xbf7bbf80,0x3e480000,0x3e480000,0x3f7b3f80,
0xbf55bf6d,0x3f0e3ec4,0x3f0e3ec4,0x3f553f6d,0xbf0ebf35,0x3f553f35,0x3f553f35,0x3f0e3f35,0xbe48bec4,0x3f7b3f6d,0x3f7b3f6d,0x3e483ec4,
0xbe950000,0xbf75bf80,0xbef1bf35,0x3f623f35,0xbf46bf0e,0xbf22bf55,0x3dc9be48,0x3f7f3f7b,0xbf7fbf6d,0xbdc9bec4,0x3f223ec4,0x3f463f6d,
0xbf62bf7b,0x3ef13e48,0x3f753f55,0x3e953f0e,0x3f6d3f80,0xbec40000,0xbf6dbf80,0x3ec40000,0x3ec43f35,0xbf6dbf35,0xbec4bf35,0x3f6d3f35,
0xbec40000,0xbf6dbf80,0x3ec40000,0x3f6d3f80,0xbf6dbf35,0xbec4bf35,0x3f6d3f35,0x3ec43f35,0x3ef10000,0x3f623f80,0xbf75bf35,0xbe95bf35,
0x3f7f3f55,0x3dc93f0e,0xbf46bf7b,0x3f223e48,0x3f223f6d,0xbf46bec4,0x3dc9bec4,0x3f7f3f6d,0xbe953e48,0xbf75bf7b,0x3f623f0e,0x3ef13f55,
0xbf55bf80,0x3f0e0000,0xbf0e0000,0xbf55bf80,0x3e48bec4,0x3f7b3f6d,0xbf7bbf6d,0x3e48bec4,0x3f7b3f35,0x3e483f35,0xbe48bf35,0x3f7b3f35,
0x3f0e3f6d,0xbf55bec4,0x3f553ec4,0x3f0e3f6d,0xbf220000,0xbf46bf80,0x3dc93f35,0xbf7fbf35,0xbf62bf7b,0x3ef1be48,0xbf75bf0e,0xbe95bf55,
0x3e95bec4,0x3f753f6d,0xbef1bf6d,0x3f623ec4,0x3f7f3f55,0xbdc93f0e,0x3f463e48,0x3f223f7b,0x3f353f80,0xbf350000,0x3f353f80,0xbf350000,
0xbf350000,0xbf35bf80,0xbf350000,0xbf35bf80,0xbf35bf80,0x3f350000,0xbf35bf80,0x3f350000,0x3f350000,0x3f353f80,0x3f350000,0x3f353f80,
0x3f460000,0x3f223f80,0x3f7f3f35,0xbdc93f35,0x3ef13f7b,0xbf62be48,0xbe953f0e,0xbf75bf55,0xbf75bec4,0xbe95bf6d,0xbf62bf6d,0x3ef1bec4,
0xbdc9bf55,0x3f7f3f0e,0x3f22be48,0x3f463f7b,0xbf0ebf80,0x3f550000,0x3f550000,0x3f0e3f80,0x3f7b3ec4,0x3e483f6d,0x3e483f6d,0xbf7bbec4,
0xbe483f35,0xbf7bbf35,0xbf7bbf35,0x3e48bf35,0xbf55bf6d,0x3f0ebec4,0x3f0ebec4,0x3f553f6d,0xbf620000,0xbef1bf80,0x3e95bf35,0x3f753f35,
0x3dc9bf55,0x3f7f3f0e,0x3f223f7b,0xbf463e48,0x3f463f6d,0xbf223ec4,0xbf7fbec4,0xbdc9bf6d,0xbf75be48,0xbe95bf7b,0x3ef1bf0e,0x3f623f55,
0x3ec43f80,0xbf6d0000,0xbec4bf80,0x3f6d0000,0xbf6dbf35,0x3ec4bf35,0x3f6d3f35,0xbec43f35,0x3f6d0000,0x3ec43f80,0xbf6d0000,0xbec4bf80,
0xbec43f35,0xbf6dbf35,0x3ec4bf35,0x3f6d3f35,0x3f750000,0x3e953f80,0xbf62bf35,0x3ef1bf35,0xbf223f0e,0xbf46bf55,0x3f7f3e48,0x3dc93f7b,
0x3dc9bf6d,0x3f7f3ec4,0xbf463ec4,0xbf22bf6d,0x3ef13f7b,0xbf623e48,0x3e95bf55,0x3f753f0e,0xbe48bf80,0x3f7b0000,0xbf7b0000,0xbe48bf80,
0x3f0e3f6d,0xbf553ec4,0x3f55bec4,0x3f0e3f6d,0xbf55bf35,0x3f0ebf35,0xbf0e3f35,0xbf55bf35,0x3f7b3ec4,0xbe483f6d,0x3e48bf6d,0x3f7b3ec4,
0xbf7f0000,0xbdc9bf80,0xbf223f35,0xbf46bf35,0x3f75be48,0x3e953f7b,0x3ef1bf55,0x3f623f0e,0xbf623ec4,0xbef1bf6d,0xbe953f6d,0xbf75bec4,
0x3f46bf0e,0x3f223f55,0x3dc9bf7b,0x3f7f3e48,0x3f80,0xbf800000,0x3f80,0xbf800000,0xbf80,0x3f800000,0xbf80,0x3f800000,
0x3f80,0xbf800000,0x3f80,0xbf800000,0xbf80,0x3f800000,0xbf80,0x3f800000,0x3f7f0000,0xbdc93f80,0x3f223f35,0xbf463f35,
0xbf75be48,0x3e95bf7b,0xbef1bf55,0x3f62bf0e,0x3f623ec4,0xbef13f6d,0x3e953f6d,0xbf753ec4,0xbf46bf0e,0x3f22bf55,0xbdc9bf7b,0x3f7fbe48,
0x3e48bf80,0x3f7b0000,0x3f7b0000,0xbe483f80,0xbf0e3f6d,0xbf55bec4,0xbf55bec4,0x3f0ebf6d,0x3f55bf35,0x3f0e3f35,0x3f0e3f35,0xbf553f35,
0xbf7b3ec4,0xbe48bf6d,0xbe48bf6d,0x3f7bbec4,0xbf750000,0x3e95bf80,0x3f62bf35,0x3ef13f35,0x3f223f0e,0xbf463f55,0xbf7f3e48,0x3dc9bf7b,
0xbdc9bf6d,0x3f7fbec4,0x3f463ec4,0xbf223f6d,0xbef13f7b,0xbf62be48,0xbe95bf55,0x3f75bf0e,0xbec43f80,0xbf6d0000,0x3ec4bf80,0x3f6d0000,
0x3f6dbf35,0x3ec43f35,0xbf6d3f35,0xbec4bf35,0xbf6d0000,0x3ec4bf80,0x3f6d0000,0xbec43f80,0x3ec43f35,0xbf6d3f35,0xbec4bf35,0x3f6dbf35,
0x3f620000,0xbef13f80,0xbe95bf35,0x3f75bf35,0xbdc9bf55,0x3f7fbf0e,0xbf223f7b,0xbf46be48,0xbf463f6d,0xbf22bec4,0x3f7fbec4,0xbdc93f6d,
0x3f75be48,0xbe953f7b,0xbef1bf0e,0x3f62bf55,0x3f0ebf80,0x3f550000,0xbf550000,0x3f0ebf80,0xbf7b3ec4,0x3e48bf6d,0xbe483f6d,0xbf7b3ec4,
0x3e483f35,0xbf7b3f35,0x3f7bbf35,0x3e483f35,0x3f55bf6d,0x3f0e3ec4,0xbf0ebec4,0x3f55bf6d,0xbf460000,0x3f22bf80,0xbf7f3f35,0xbdc9bf35,
0xbef13f7b,0xbf623e48,0x3e953f0e,0xbf753f55,0x3f75bec4,0xbe953f6d,0x3f62bf6d,0x3ef13ec4,0x3dc9bf55,0x3f7fbf0e,0xbf22be48,0x3f46bf7b,
0xbf353f80,0xbf350000,0xbf353f80,0xbf350000,0x3f350000,0xbf353f80,0x3f350000,0xbf353f80,0x3f35bf80,0x3f350000,0x3f35bf80,0x3f350000,
0xbf350000,0x3f35bf80,0xbf350000,0x3f35bf80,0x3f220000,0xbf463f80,0xbdc93f35,0xbf7f3f35,0x3f62bf7b,0x3ef13e48,0x3f75bf0e,0xbe953f55,
0xbe95bec4,0x3f75bf6d,0x3ef1bf6d,0x3f62bec4,0xbf7f3f55,0xbdc9bf0e,0xbf463e48,0x3f22bf7b,0x3f55bf80,0x3f0e0000,0x3f0e0000,0xbf553f80,
0xbe48bec4,0x3f7bbf6d,0x3f7bbf6d,0x3e483ec4,0xbf7b3f35,0x3e48bf35,0x3e48bf35,0x3f7bbf35,0xbf0e3f6d,0xbf553ec4,0xbf553ec4,0x3f0ebf6d,
0xbef10000,0x3f62bf80,0x3f75bf35,0xbe953f35,0xbf7f3f55,0x3dc9bf0e,0x3f46bf7b,0x3f22be48,0xbf223f6d,0xbf463ec4,0xbdc9bec4,0x3f7fbf6d,
0x3e953e48,0xbf753f7b,0xbf623f0e,0x3ef1bf55,0xbf6d3f80,0xbec40000,0x3f6dbf80,0x3ec40000,0xbec43f35,0xbf6d3f35,0x3ec4bf35,0x3f6dbf35,
0x3ec40000,0xbf6d3f80,0xbec40000,0x3f6dbf80,0x3f6dbf35,0xbec43f35,0xbf6d3f35,0x3ec4bf35,0x3e950000,0xbf753f80,0x3ef1bf35,0x3f62bf35,
0x3f46bf0e,0xbf223f55,0xbdc9be48,0x3f7fbf7b,0x3f7fbf6d,0xbdc93ec4,0xbf223ec4,0x3f46bf6d,0x3f62bf7b,0x3ef1be48,0xbf753f55,0x3e95bf0e,
0x3f7bbf80,0x3e480000,0xbe480000,0x3f7bbf80,0x3f55bf6d,0x3f0ebec4,0xbf0e3ec4,0x3f55bf6d,0x3f0ebf35,0x3f55bf35,0xbf553f35,0x3f0ebf35,
0x3e48bec4,0x3f7bbf6d,0xbf7b3f6d,0x3e48bec4,0xbdc90000,0x3f7fbf80,0xbf463f35,0x3f22bf35,0xbe953e48,0x3f75bf7b,0xbf623f55,0x3ef1bf0e,
0xbef13ec4,0x3f62bf6d,0xbf753f6d,0x3e95bec4,0xbf223f0e,0x3f46bf55,0xbf7f3f7b,0x3dc9be48,0x40003f80,0x3fb53f80,0x3f80,0xbfb53f80,
0x40004000,0xbfb50000,0x0,0xbfb5c000,0x40004000,0xbfb5c000,0x0,0x3fb50000,0x40004000,0x3fb50000,0x0,0x3fb54000,
0x3fff3f80,0x3fa23f80,0xbe49bf80,0xbfc6bf80,0x3ff53ffb,0xbfe2bec8,0xbf15bec8,0xbf71bffb,0x3fe23fed,0xbf15bfed,0xbf71bf44,0x3ff53f44,
0x3fc63fd5,0x3fff3f8e,0xbfa2bf8e,0x3e493fd5,0x3ffb3f80,0x3f8e3f80,0xbec83f80,0xbfd53f80,0x3fd53fed,0xbffbbf44,0xbf8ebf44,0xbec8bfed,
0x3f8e3fb5,0x3ec8bfb5,0xbfd5bfb5,0x3ffb3fb5,0x3ec83f44,0x3fd53fed,0xbffbbfed,0xbf8e3f44,0x3ff53f80,0x3f713f80,0xbf15bf80,0xbfe2bf80,
0x3fa23fd5,0xbfffbf8e,0xbfc6bf8e,0x3e49bfd5,0x3e493f44,0x3fa2bf44,0xbfffbfed,0x3fc63fed,0xbf71bec8,0x3f153ffb,0xbfe2bffb,0xbff5bec8,
0x3fed3f80,0x3f443f80,0xbf443f80,0xbfed3f80,0x3f443fb5,0xbfedbfb5,0xbfedbfb5,0x3f44bfb5,0xbf440000,0x3fed0000,0xbfedc000,0x3f444000,
0xbfedbfb5,0xbf443fb5,0xbf44bfb5,0xbfedbfb5,0x3fe23f80,0x3f153f80,0xbf71bf80,0xbff5bf80,0x3e493f8e,0xbfc6bfd5,0xbfffbfd5,0x3fa2bf8e,
0xbfc6bf44,0x3fff3f44,0xbfa2bfed,0xbe493fed,0xbff5bffb,0xbfe23ec8,0x3f15bec8,0xbf71bffb,0x3fd53f80,0x3ec83f80,0xbf8e3f80,0xbffb3f80,
0xbec83f44,0xbf8ebfed,0xbffbbfed,0x3fd5bf44,0xbffbbfb5,0x3fd53fb5,0xbec8bfb5,0xbf8e3fb5,0xbf8ebfed,0xbffbbf44,0x3fd53f44,0x3ec8bfed,
0x3fc63f80,0x3e493f80,0xbfa2bf80,0xbfffbf80,0xbf713ec8,0xbf15bffb,0xbfe2bffb,0x3ff5bec8,0xbff5bfed,0x3f713fed,0x3f15bf44,0xbfe23f44,
0x3e49bf8e,0xbfa2bfd5,0x3fff3fd5,0x3fc6bf8e,0x3f80,0xbfb53f80,0xc0003f80,0xbfb53f80,0xc000,0x3fb50000,0x40000000,0xbfb54000,
0x4000,0x3fb5c000,0xc0000000,0x3fb50000,0xc000,0xbfb50000,0x40000000,0x3fb5c000,0xbe493f80,0xbfc63f80,0xbfffbf80,0xbfa2bf80,
0x3f15bffb,0x3f713ec8,0x3ff53ec8,0xbfe23ffb,0xbf713fed,0x3ff5bfed,0xbfe2bf44,0x3f153f44,0x3fa2bfd5,0xbe49bf8e,0x3fc63f8e,0x3fffbfd5,
0xbec83f80,0xbfd53f80,0xbffb3f80,0xbf8e3f80,0x3f8ebfed,0x3ec83f44,0x3fd53f44,0xbffb3fed,0xbfd53fb5,0x3ffbbfb5,0xbf8ebfb5,0xbec83fb5,
0x3ffbbf44,0x3f8ebfed,0x3ec83fed,0x3fd5bf44,0xbf153f80,0xbfe23f80,0xbff5bf80,0xbf71bf80,0x3fc6bfd5,0xbe493f8e,0x3fa23f8e,0xbfff3fd5,
0xbfff3f44,0x3fc6bf44,0xbe49bfed,0xbfa23fed,0x3fe23ec8,0x3ff5bffb,0xbf713ffb,0x3f153ec8,0xbf443f80,0xbfed3f80,0xbfed3f80,0xbf443f80,
0x3fedbfb5,0xbf443fb5,0x3f443fb5,0xbfed3fb5,0xbfed0000,0x3f440000,0x3f44c000,0xbfed4000,0x3f443fb5,0x3fedbfb5,0xbfed3fb5,0xbf443fb5,
0xbf713f80,0xbff53f80,0xbfe2bf80,0xbf15bf80,0x3fffbf8e,0xbfa23fd5,0x3e493fd5,0xbfc63f8e,0xbfa2bf44,0xbe493f44,0x3fc6bfed,0xbfff3fed,
0xbf153ffb,0x3f71bec8,0xbff53ec8,0xbfe23ffb,0xbf8e3f80,0xbffb3f80,0xbfd53f80,0xbec83f80,0x3ffbbf44,0xbfd53fed,0xbec83fed,0xbf8e3f44,
0xbec8bfb5,0xbf8e3fb5,0x3ffbbfb5,0xbfd53fb5,0xbfd53fed,0xbec83f44,0xbf8ebf44,0xbffb3fed,0xbfa23f80,0xbfff3f80,0xbfc6bf80,0xbe49bf80,
0x3fe2bec8,0xbff53ffb,0xbf713ffb,0xbf153ec8,0x3f15bfed,0xbfe23fed,0x3ff5bf44,0xbf713f44,0xbfff3f8e,0xbfc63fd5,0x3e49bfd5,0xbfa23f8e,
0xc0003f80,0xbfb53f80,0x3f80,0x3fb53f80,0xc0004000,0x3fb50000,0x0,0x3fb5c000,0xc0004000,0x3fb5c000,0x0,0xbfb50000,
0xc0004000,0xbfb50000,0x0,0xbfb54000,0xbfff3f80,0xbfa23f80,0x3e49bf80,0x3fc6bf80,0xbff53ffb,0x3fe2bec8,0x3f15bec8,0x3f71bffb,
0xbfe23fed,0x3f15bfed,0x3f71bf44,0xbff53f44,0xbfc63fd5,0xbfff3f8e,0x3fa2bf8e,0xbe493fd5,0xbffb3f80,0xbf8e3f80,0x3ec83f80,0x3fd53f80,
0xbfd53fed,0x3ffbbf44,0x3f8ebf44,0x3ec8bfed,0xbf8e3fb5,0xbec8bfb5,0x3fd5bfb5,0xbffb3fb5,0xbec83f44,0xbfd53fed,0x3ffbbfed,0x3f8e3f44,
0xbff53f80,0xbf713f80,0x3f15bf80,0x3fe2bf80,0xbfa23fd5,0x3fffbf8e,0x3fc6bf8e,0xbe49bfd5,0xbe493f44,0xbfa2bf44,0x3fffbfed,0xbfc63fed,
0x3f71bec8,0xbf153ffb,0x3fe2bffb,0x3ff5bec8,0xbfed3f80,0xbf443f80,0x3f443f80,0x3fed3f80,0xbf443fb5,0x3fedbfb5,0x3fedbfb5,0xbf44bfb5,
0x3f440000,0xbfed0000,0x3fedc000,0xbf444000,0x3fedbfb5,0x3f443fb5,0x3f44bfb5,0x3fedbfb5,0xbfe23f80,0xbf153f80,0x3f71bf80,0x3ff5bf80,
0xbe493f8e,0x3fc6bfd5,0x3fffbfd5,0xbfa2bf8e,0x3fc6bf44,0xbfff3f44,0x3fa2bfed,0x3e493fed,0x3ff5bffb,0x3fe23ec8,0xbf15bec8,0x3f71bffb,
0xbfd53f80,0xbec83f80,0x3f8e3f80,0x3ffb3f80,0x3ec83f44,0x3f8ebfed,0x3ffbbfed,0xbfd5bf44,0x3ffbbfb5,0xbfd53fb5,0x3ec8bfb5,0x3f8e3fb5,
0x3f8ebfed,0x3ffbbf44,0xbfd53f44,0xbec8bfed,0xbfc63f80,0xbe493f80,0x3fa2bf80,0x3fffbf80,0x3f713ec8,0x3f15bffb,0x3fe2bffb,0xbff5bec8,
0x3ff5bfed,0xbf713fed,0xbf15bf44,0x3fe23f44,0xbe49bf8e,0x3fa2bfd5,0xbfff3fd5,0xbfc6bf8e,0x3f80,0x3fb53f80,0x40003f80,0x3fb53f80,
0xc000,0xbfb50000,0xc0000000,0x3fb54000,0x4000,0xbfb5c000,0x40000000,0xbfb50000,0xc000,0x3fb50000,0xc0000000,0xbfb5c000,
0x3e493f80,0x3fc63f80,0x3fffbf80,0x3fa2bf80,0xbf15bffb,0xbf713ec8,0xbff53ec8,0x3fe23ffb,0x3f713fed,0xbff5bfed,0x3fe2bf44,0xbf153f44,
0xbfa2bfd5,0x3e49bf8e,0xbfc63f8e,0xbfffbfd5,0x3ec83f80,0x3fd53f80,0x3ffb3f80,0x3f8e3f80,0xbf8ebfed,0xbec83f44,0xbfd53f44,0x3ffb3fed,
0x3fd53fb5,0xbffbbfb5,0x3f8ebfb5,0x3ec83fb5,0xbffbbf44,0xbf8ebfed,0xbec83fed,0xbfd5bf44,0x3f153f80,0x3fe23f80,0x3ff5bf80,0x3f71bf80,
0xbfc6bfd5,0x3e493f8e,0xbfa23f8e,0x3fff3fd5,0x3fff3f44,0xbfc6bf44,0x3e49bfed,0x3fa23fed,0xbfe23ec8,0xbff5bffb,0x3f713ffb,0xbf153ec8,
0x3f443f80,0x3fed3f80,0x3fed3f80,0x3f443f80,0xbfedbfb5,0x3f443fb5,0xbf443fb5,0x3fed3fb5,0x3fed0000,0xbf440000,0xbf44c000,0x3fed4000,
0xbf443fb5,0xbfedbfb5,0x3fed3fb5,0x3f443fb5,0x3f713f80,0x3ff53f80,0x3fe2bf80,0x3f15bf80,0xbfffbf8e,0x3fa23fd5,0xbe493fd5,0x3fc63f8e,
0x3fa2bf44,0x3e493f44,0xbfc6bfed,0x3fff3fed,0x3f153ffb,0xbf71bec8,0x3ff53ec8,0x3fe23ffb,0x3f8e3f80,0x3ffb3f80,0x3fd53f80,0x3ec83f80,
0xbffbbf44,0x3fd53fed,0x3ec83fed,0x3f8e3f44,0x3ec8bfb5,0x3f8e3fb5,0xbffbbfb5,0x3fd53fb5,0x3fd53fed,0x3ec83f44,0x3f8ebf44,0x3ffb3fed,
0x3fa23f80,0x3fff3f80,0x3fc6bf80,0x3e49bf80,0xbfe2bec8,0x3ff53ffb,0x3f713ffb,0x3f153ec8,0xbf15bfed,0x3fe23fed,0xbff5bf44,0x3f713f44,
0x3fff3f8e,0x3fc63fd5,0xbe49bfd5,0x3fa23f8e,0x40004000,0x3fb54000,0x0,0xbfb50000,0x40004000,0xbfb50000,0x0,0xbfb5c000,
0x40004000,0xbfb5c000,0x0,0x3fb50000,0x40004000,0x3fb50000,0x0,0x3fb54000,0x3fa23fb5,0xbe493fb5,0xbfc6bfb5,0xbfffbfb5,
0x3f713f8e,0xbff5bfd5,0xbfe2bfd5,0x3f15bf8e,0x3f153f44,0x3f71bf44,0xbff5bfed,0x3fe23fed,0x3e493ec8,0x3fc63ffb,0xbfffbffb,0xbfa23ec8,
0xbec80000,0xbfd50000,0xbffbc000,0xbf8ec000,0xbf8ebf44,0xbec8bfed,0xbfd5bfed,0x3ffb3f44,0xbfd5bfb5,0x3ffb3fb5,0xbf8ebfb5,0xbec83fb5,
0xbffbbfed,0xbf8e3f44,0xbec8bf44,0xbfd5bfed,0xbfe2bfb5,0xbff5bfb5,0xbf71bfb5,0x3f15bfb5,0xbfffbffb,0x3fc6bec8,0x3e49bec8,0x3fa23ffb,
0xbfc6bfed,0x3e493fed,0x3fa23f44,0xbfffbf44,0xbf15bf8e,0xbfe2bfd5,0x3ff53fd5,0x3f71bf8e,0xbfedc000,0xbf44c000,0x3f440000,0x3fed0000,
0xbf44bfb5,0x3fed3fb5,0x3fed3fb5,0xbf443fb5,0x3f440000,0xbfed0000,0x3fed4000,0xbf44c000,0x3fed3fb5,0x3f44bfb5,0x3f443fb5,0x3fed3fb5,
0xbf15bfb5,0x3f71bfb5,0x3ff53fb5,0x3fe23fb5,0x3fa23ec8,0x3e493ffb,0x3fc63ffb,0xbfffbec8,0x3fff3fed,0xbfa2bfed,0xbe493f44,0x3fc6bf44,
0x3f713fd5,0x3ff53f8e,0xbfe2bf8e,0xbf153fd5,0x3f8e0000,0x3ffb0000,0x3fd54000,0x3ec84000,0x3ffb3fed,0xbfd53f44,0xbec83f44,0xbf8ebfed,
0x3ec83fb5,0x3f8ebfb5,0xbffbbfb5,0x3fd53fb5,0xbfd5bf44,0xbec83fed,0xbf8ebfed,0xbffbbf44,0x3fff3fb5,0x3fc63fb5,0x3e493fb5,0xbfa23fb5,
0x3f153fd5,0xbfe2bf8e,0xbff5bf8e,0x3f71bfd5,0xbfe2bf44,0x3ff53f44,0xbf71bfed,0xbf153fed,0xbfa2bffb,0xbfffbec8,0x3fc63ec8,0x3e49bffb,
0x4000,0xbfb54000,0xc0000000,0xbfb50000,0xc000,0x3fb50000,0x40000000,0xbfb54000,0x4000,0x3fb5c000,0xc0000000,0x3fb50000,
0xc000,0xbfb50000,0x40000000,0x3fb5c000,0xbfc63fb5,0xbfff3fb5,0xbfa2bfb5,0x3e49bfb5,0x3fe2bf8e,0xbf153fd5,0x3f713fd5,0xbff53f8e,
0xbff53f44,0x3fe2bf44,0xbf15bfed,0xbf713fed,0x3fffbec8,0x3fa2bffb,0x3e493ffb,0x3fc6bec8,0xbffb0000,0xbf8e0000,0x3ec8c000,0x3fd5c000,
0x3fd53f44,0xbffb3fed,0xbf8e3fed,0xbec8bf44,0xbf8ebfb5,0xbec83fb5,0x3fd5bfb5,0xbffb3fb5,0x3ec83fed,0x3fd5bf44,0xbffb3f44,0xbf8e3fed,
0xbf71bfb5,0x3f15bfb5,0x3fe2bfb5,0x3ff5bfb5,0xbe493ffb,0xbfa23ec8,0xbfff3ec8,0x3fc6bffb,0x3fa2bfed,0xbfff3fed,0x3fc63f44,0xbe49bf44,
0xbff53f8e,0xbf713fd5,0xbf15bfd5,0xbfe23f8e,0x3f44c000,0x3fedc000,0x3fed0000,0x3f440000,0xbfed3fb5,0x3f44bfb5,0xbf44bfb5,0x3fedbfb5,
0x3fed0000,0xbf440000,0xbf444000,0x3fedc000,0xbf44bfb5,0xbfed3fb5,0x3fedbfb5,0x3f44bfb5,0x3ff5bfb5,0x3fe2bfb5,0x3f153fb5,0xbf713fb5,
0xbfc6bec8,0x3fffbffb,0x3fa2bffb,0x3e493ec8,0xbe493fed,0x3fc6bfed,0xbfff3f44,0x3fa2bf44,0x3fe2bfd5,0x3f15bf8e,0x3f713f8e,0x3ff5bfd5,
0x3fd50000,0x3ec80000,0xbf8e4000,0xbffb4000,0x3ec8bfed,0x3f8ebf44,0x3ffbbf44,0xbfd53fed,0xbffb3fb5,0x3fd5bfb5,0xbec8bfb5,0xbf8e3fb5,
0x3f8e3f44,0x3ffbbfed,0xbfd53fed,0xbec83f44,0x3e493fb5,0xbfa23fb5,0xbfff3fb5,0xbfc63fb5,0x3ff5bfd5,0xbf713f8e,0x3f153f8e,0xbfe23fd5,
0xbf71bf44,0xbf153f44,0x3fe2bfed,0xbff53fed,0xbfc63ffb,0xbe493ec8,0xbfa2bec8,0xbfff3ffb,0xc0004000,0xbfb54000,0x0,0x3fb50000,
0xc0004000,0x3fb50000,0x0,0x3fb5c000,0xc0004000,0x3fb5c000,0x0,0xbfb50000,0xc0004000,0xbfb50000,0x0,0xbfb54000,
0xbfa23fb5,0x3e493fb5,0x3fc6bfb5,0x3fffbfb5,0xbf713f8e,0x3ff5bfd5,0x3fe2bfd5,0xbf15bf8e,0xbf153f44,0xbf71bf44,0x3ff5bfed,0xbfe23fed,
0xbe493ec8,0xbfc63ffb,0x3fffbffb,0x3fa23ec8,0x3ec80000,0x3fd50000,0x3ffbc000,0x3f8ec000,0x3f8ebf44,0x3ec8bfed,0x3fd5bfed,0xbffb3f44,
0x3fd5bfb5,0xbffb3fb5,0x3f8ebfb5,0x3ec83fb5,0x3ffbbfed,0x3f8e3f44,0x3ec8bf44,0x3fd5bfed,0x3fe2bfb5,0x3ff5bfb5,0x3f71bfb5,0xbf15bfb5,
0x3fffbffb,0xbfc6bec8,0xbe49bec8,0xbfa23ffb,0x3fc6bfed,0xbe493fed,0xbfa23f44,0x3fffbf44,0x3f15bf8e,0x3fe2bfd5,0xbff53fd5,0xbf71bf8e,
0x3fedc000,0x3f44c000,0xbf440000,0xbfed0000,0x3f44bfb5,0xbfed3fb5,0xbfed3fb5,0x3f443fb5,0xbf440000,0x3fed0000,0xbfed4000,0x3f44c000,
0xbfed3fb5,0xbf44bfb5,0xbf443fb5,0xbfed3fb5,0x3f15bfb5,0xbf71bfb5,0xbff53fb5,0xbfe23fb5,0xbfa23ec8,0xbe493ffb,0xbfc63ffb,0x3fffbec8,
0xbfff3fed,0x3fa2bfed,0x3e493f44,0xbfc6bf44,0xbf713fd5,0xbff53f8e,0x3fe2bf8e,0x3f153fd5,0xbf8e0000,0xbffb0000,0xbfd54000,0xbec84000,
0xbffb3fed,0x3fd53f44,0x3ec83f44,0x3f8ebfed,0xbec83fb5,0xbf8ebfb5,0x3ffbbfb5,0xbfd53fb5,0x3fd5bf44,0x3ec83fed,0x3f8ebfed,0x3ffbbf44,
0xbfff3fb5,0xbfc63fb5,0xbe493fb5,0x3fa23fb5,0xbf153fd5,0x3fe2bf8e,0x3ff5bf8e,0xbf71bfd5,0x3fe2bf44,0xbff53f44,0x3f71bfed,0x3f153fed,
0x3fa2bffb,0x3fffbec8,0xbfc63ec8,0xbe49bffb,0x4000,0x3fb54000,0x40000000,0x3fb50000,0xc000,0xbfb50000,0xc0000000,0x3fb54000,
0x4000,0xbfb5c000,0x40000000,0xbfb50000,0xc000,0x3fb50000,0xc0000000,0xbfb5c000,0x3fc63fb5,0x3fff3fb5,0x3fa2bfb5,0xbe49bfb5,
0xbfe2bf8e,0x3f153fd5,0xbf713fd5,0x3ff53f8e,0x3ff53f44,0xbfe2bf44,0x3f15bfed,0x3f713fed,0xbfffbec8,0xbfa2bffb,0xbe493ffb,0xbfc6bec8,
0x3ffb0000,0x3f8e0000,0xbec8c000,0xbfd5c000,0xbfd53f44,0x3ffb3fed,0x3f8e3fed,0x3ec8bf44,0x3f8ebfb5,0x3ec83fb5,0xbfd5bfb5,0x3ffb3fb5,
0xbec83fed,0xbfd5bf44,0x3ffb3f44,0x3f8e3fed,0x3f71bfb5,0xbf15bfb5,0xbfe2bfb5,0xbff5bfb5,0x3e493ffb,0x3fa23ec8,0x3fff3ec8,0xbfc6bffb,
0xbfa2bfed,0x3fff3fed,0xbfc63f44,0x3e49bf44,0x3ff53f8e,0x3f713fd5,0x3f15bfd5,0x3fe23f8e,0xbf44c000,0xbfedc000,0xbfed0000,0xbf440000,
0x3fed3fb5,0xbf44bfb5,0x3f44bfb5,0xbfedbfb5,0xbfed0000,0x3f440000,0x3f444000,0xbfedc000,0x3f44bfb5,0x3fed3fb5,0xbfedbfb5,0xbf44bfb5,
0xbff5bfb5,0xbfe2bfb5,0xbf153fb5,0x3f713fb5,0x3fc6bec8,0xbfffbffb,0xbfa2bffb,0xbe493ec8,0x3e493fed,0xbfc6bfed,0x3fff3f44,0xbfa2bf44,
0xbfe2bfd5,0xbf15bf8e,0xbf713f8e,0xbff5bfd5,0xbfd50000,0xbec80000,0x3f8e4000,0x3ffb4000,0xbec8bfed,0xbf8ebf44,0xbffbbf44,0x3fd53fed,
0x3ffb3fb5,0xbfd5bfb5,0x3ec8bfb5,0x3f8e3fb5,0xbf8e3f44,0xbffbbfed,0x3fd53fed,0x3ec83f44,0xbe493fb5,0x3fa23fb5,0x3fff3fb5,0x3fc63fb5,
0xbff5bfd5,0x3f713f8e,0xbf153f8e,0x3fe23fd5,0x3f71bf44,0x3f153f44,0xbfe2bfed,0x3ff53fed,0x3fc63ffb,0x3e493ec8,0x3fa2bec8,0x3fff3ffb,
0x40004000,0x3fb54000,0x0,0xbfb50000,0x40004000,0xbfb50000,0x0,0xbfb5c000,0x40004000,0xbfb5c000,0x0,0x3fb50000,
0x40004000,0x3fb50000,0x0,0x3fb54000,0xbe490000,0xbfc60000,0xbfffc000,0xbfa2c000,0xbf15bec8,0xbf71bffb,0xbff5bffb,0x3fe23ec8,
0xbf71bf44,0x3ff53f44,0xbfe2bfed,0x3f153fed,0xbfa2bf8e,0x3e493fd5,0xbfc6bfd5,0xbfffbf8e,0xbffbc000,0xbf8ec000,0x3ec80000,0x3fd50000,
0xbfd5bfed,0x3ffb3f44,0x3f8e3f44,0x3ec83fed,0xbf8ebfb5,0xbec83fb5,0x3fd53fb5,0xbffbbfb5,0xbec8bf44,0xbfd5bfed,0x3ffb3fed,0x3f8ebf44,
0x3f150000,0x3fe20000,0x3ff54000,0x3f714000,0x3fc63f8e,0xbe493fd5,0x3fa23fd5,0xbfffbf8e,0x3fff3fed,0xbfc6bfed,0x3e493f44,0x3fa2bf44,
0x3fe23ffb,0x3ff53ec8,0xbf71bec8,0x3f153ffb,0x3fed4000,0x3f444000,0xbf440000,0xbfed0000,0x3f443fb5,0xbfedbfb5,0xbfedbfb5,0x3f44bfb5,
0xbf440000,0x3fed0000,0xbfedc000,0x3f444000,0xbfedbfb5,0xbf443fb5,0xbf44bfb5,0xbfedbfb5,0xbf710000,0xbff50000,0xbfe2c000,0xbf15c000,
0xbfffbfd5,0x3fa2bf8e,0xbe49bf8e,0x3fc63fd5,0xbfa2bfed,0xbe493fed,0x3fc63f44,0xbfffbf44,0x3f15bec8,0xbf71bffb,0x3ff53ffb,0x3fe2bec8,
0xbfd5c000,0xbec8c000,0x3f8e0000,0x3ffb0000,0x3ec8bf44,0x3f8e3fed,0x3ffb3fed,0xbfd53f44,0x3ffb3fb5,0xbfd5bfb5,0x3ec83fb5,0x3f8ebfb5,
0x3f8e3fed,0x3ffb3f44,0xbfd5bf44,0xbec83fed,0x3fa20000,0x3fff0000,0x3fc64000,0x3e494000,0x3fe23ffb,0xbff53ec8,0xbf713ec8,0xbf15bffb,
0xbf153f44,0x3fe2bf44,0xbff5bfed,0x3f713fed,0xbfffbfd5,0xbfc63f8e,0x3e49bf8e,0xbfa2bfd5,0x4000,0xbfb54000,0xc0000000,0xbfb50000,
0xc000,0x3fb50000,0x40000000,0xbfb54000,0x4000,0x3fb5c000,0xc0000000,0x3fb50000,0xc000,0xbfb50000,0x40000000,0x3fb5c000,
0xbfff0000,0xbfa20000,0x3e49c000,0x3fc6c000,0x3ff53ec8,0xbfe23ffb,0xbf153ffb,0xbf71bec8,0xbfe2bf44,0x3f153f44,0x3f71bfed,0xbff53fed,
0x3fc63f8e,0x3fffbfd5,0xbfa23fd5,0x3e493f8e,0x3ec8c000,0x3fd5c000,0x3ffb0000,0x3f8e0000,0xbf8e3fed,0xbec8bf44,0xbfd5bf44,0x3ffbbfed,
0x3fd5bfb5,0xbffb3fb5,0x3f8e3fb5,0x3ec8bfb5,0xbffb3f44,0xbf8e3fed,0xbec8bfed,0xbfd53f44,0x3ff50000,0x3f710000,0xbf154000,0xbfe24000,
0xbfa2bf8e,0x3fffbfd5,0x3fc6bfd5,0xbe493f8e,0x3e493fed,0x3fa2bfed,0xbfff3f44,0x3fc6bf44,0x3f71bffb,0xbf15bec8,0x3fe23ec8,0x3ff5bffb,
0xbf444000,0xbfed4000,0xbfed0000,0xbf440000,0x3fedbfb5,0xbf443fb5,0x3f443fb5,0xbfed3fb5,0xbfed0000,0x3f440000,0x3f44c000,0xbfed4000,
0x3f443fb5,0x3fedbfb5,0xbfed3fb5,0xbf443fb5,0xbfe20000,0xbf150000,0x3f71c000,0x3ff5c000,0x3e493fd5,0xbfc63f8e,0xbfff3f8e,0x3fa2bfd5,
0x3fc6bfed,0xbfff3fed,0x3fa23f44,0x3e49bf44,0xbff53ec8,0xbfe23ffb,0x3f15bffb,0xbf713ec8,0x3f8ec000,0x3ffbc000,0x3fd50000,0x3ec80000,
0xbffb3f44,0x3fd5bfed,0x3ec8bfed,0x3f8ebf44,0x3ec83fb5,0x3f8ebfb5,0xbffb3fb5,0x3fd5bfb5,0x3fd5bfed,0x3ec8bf44,0x3f8e3f44,0x3ffbbfed,
0x3fc60000,0x3e490000,0xbfa24000,0xbfff4000,0x3f71bffb,0x3f15bec8,0x3fe2bec8,0xbff53ffb,0xbff53f44,0x3f71bf44,0x3f15bfed,0xbfe23fed,
0xbe493fd5,0x3fa2bf8e,0xbfff3f8e,0xbfc63fd5,0xc0004000,0xbfb54000,0x0,0x3fb50000,0xc0004000,0x3fb50000,0x0,0x3fb5c000,
0xc0004000,0x3fb5c000,0x0,0xbfb50000,0xc0004000,0xbfb50000,0x0,0xbfb54000,0x3e490000,0x3fc60000,0x3fffc000,0x3fa2c000,
0x3f15bec8,0x3f71bffb,0x3ff5bffb,0xbfe23ec8,0x3f71bf44,0xbff53f44,0x3fe2bfed,0xbf153fed,0x3fa2bf8e,0xbe493fd5,0x3fc6bfd5,0x3fffbf8e,
0x3ffbc000,0x3f8ec000,0xbec80000,0xbfd50000,0x3fd5bfed,0xbffb3f44,0xbf8e3f44,0xbec83fed,0x3f8ebfb5,0x3ec83fb5,0xbfd53fb5,0x3ffbbfb5,
0x3ec8bf44,0x3fd5bfed,0xbffb3fed,0xbf8ebf44,0xbf150000,0xbfe20000,0xbff54000,0xbf714000,0xbfc63f8e,0x3e493fd5,0xbfa23fd5,0x3fffbf8e,
0xbfff3fed,0x3fc6bfed,0xbe493f44,0xbfa2bf44,0xbfe23ffb,0xbff53ec8,0x3f71bec8,0xbf153ffb,0xbfed4000,0xbf444000,0x3f440000,0x3fed0000,
0xbf443fb5,0x3fedbfb5,0x3fedbfb5,0xbf44bfb5,0x3f440000,0xbfed0000,0x3fedc000,0xbf444000,0x3fedbfb5,0x3f443fb5,0x3f44bfb5,0x3fedbfb5,
0x3f710000,0x3ff50000,0x3fe2c000,0x3f15c000,0x3fffbfd5,0xbfa2bf8e,0x3e49bf8e,0xbfc63fd5,0x3fa2bfed,0x3e493fed,0xbfc63f44,0x3fffbf44,
0xbf15bec8,0x3f71bffb,0xbff53ffb,0xbfe2bec8,0x3fd5c000,0x3ec8c000,0xbf8e0000,0xbffb0000,0xbec8bf44,0xbf8e3fed,0xbffb3fed,0x3fd53f44,
0xbffb3fb5,0x3fd5bfb5,0xbec83fb5,0xbf8ebfb5,0xbf8e3fed,0xbffb3f44,0x3fd5bf44,0x3ec83fed,0xbfa20000,0xbfff0000,0xbfc64000,0xbe494000,
0xbfe23ffb,0x3ff53ec8,0x3f713ec8,0x3f15bffb,0x3f153f44,0xbfe2bf44,0x3ff5bfed,0xbf713fed,0x3fffbfd5,0x3fc63f8e,0xbe49bf8e,0x3fa2bfd5,
0x4000,0x3fb54000,0x40000000,0x3fb50000,0xc000,0xbfb50000,0xc0000000,0x3fb54000,0x4000,0xbfb5c000,0x40000000,0xbfb50000,
0xc000,0x3fb50000,0xc0000000,0xbfb5c000,0x3fff0000,0x3fa20000,0xbe49c000,0xbfc6c000,0xbff53ec8,0x3fe23ffb,0x3f153ffb,0x3f71bec8,
0x3fe2bf44,0xbf153f44,0xbf71bfed,0x3ff53fed,0xbfc63f8e,0xbfffbfd5,0x3fa23fd5,0xbe493f8e,0xbec8c000,0xbfd5c000,0xbffb0000,0xbf8e0000,
0x3f8e3fed,0x3ec8bf44,0x3fd5bf44,0xbffbbfed,0xbfd5bfb5,0x3ffb3fb5,0xbf8e3fb5,0xbec8bfb5,0x3ffb3f44,0x3f8e3fed,0x3ec8bfed,0x3fd53f44,
0xbff50000,0xbf710000,0x3f154000,0x3fe24000,0x3fa2bf8e,0xbfffbfd5,0xbfc6bfd5,0x3e493f8e,0xbe493fed,0xbfa2bfed,0x3fff3f44,0xbfc6bf44,
0xbf71bffb,0x3f15bec8,0xbfe23ec8,0xbff5bffb,0x3f444000,0x3fed4000,0x3fed0000,0x3f440000,0xbfedbfb5,0x3f443fb5,0xbf443fb5,0x3fed3fb5,
0x3fed0000,0xbf440000,0xbf44c000,0x3fed4000,0xbf443fb5,0xbfedbfb5,0x3fed3fb5,0x3f443fb5,0x3fe20000,0x3f150000,0xbf71c000,0xbff5c000,
0xbe493fd5,0x3fc63f8e,0x3fff3f8e,0xbfa2bfd5,0xbfc6bfed,0x3fff3fed,0xbfa23f44,0xbe49bf44,0x3ff53ec8,0x3fe23ffb,0xbf15bffb,0x3f713ec8,
0xbf8ec000,0xbffbc000,0xbfd50000,0xbec80000,0x3ffb3f44,0xbfd5bfed,0xbec8bfed,0xbf8ebf44,0xbec83fb5,0xbf8ebfb5,0x3ffb3fb5,0xbfd5bfb5,
0xbfd5bfed,0xbec8bf44,0xbf8e3f44,0xbffbbfed,0xbfc60000,0xbe490000,0x3fa24000,0x3fff4000,0xbf71bffb,0xbf15bec8,0xbfe2bec8,0x3ff53ffb,
0x3ff53f44,0xbf71bf44,0xbf15bfed,0x3fe23fed,0x3e493fd5,0xbfa2bf8e,0x3fff3f8e,0x3fc63fd5,0x40004000,0x3fb54000,0x0,0xbfb50000,
0x40004000,0xbfb50000,0x0,0xbfb5c000,0x40004000,0xbfb5c000,0x0,0x3fb50000,0x40004000,0x3fb50000,0x0,0x3fb54000,
0xbfc6bfb5,0xbfffbfb5,0xbfa2bfb5,0x3e49bfb5,0xbfe2bfd5,0x3f15bf8e,0xbf71bf8e,0x3ff53fd5,0xbff5bfed,0x3fe23fed,0xbf15bf44,0xbf713f44,
0xbfffbffb,0xbfa23ec8,0xbe49bec8,0xbfc6bffb,0x3ec80000,0x3fd50000,0x3ffb4000,0x3f8e4000,0x3f8e3f44,0x3ec83fed,0x3fd53fed,0xbffbbf44,
0x3fd53fb5,0xbffbbfb5,0x3f8e3fb5,0x3ec8bfb5,0x3ffb3fed,0x3f8ebf44,0x3ec83f44,0x3fd53fed,0x3f713fb5,0xbf153fb5,0xbfe2bfb5,0xbff5bfb5,
0xbe493ec8,0xbfa2bffb,0xbfffbffb,0x3fc6bec8,0xbfa2bf44,0x3fff3f44,0xbfc6bfed,0x3e493fed,0xbff5bfd5,0xbf713f8e,0xbf15bf8e,0xbfe2bfd5,
0xbfedc000,0xbf44c000,0x3f440000,0x3fed0000,0xbf44bfb5,0x3fed3fb5,0x3fed3fb5,0xbf443fb5,0x3f440000,0xbfed0000,0x3fed4000,0xbf44c000,
0x3fed3fb5,0x3f44bfb5,0x3f443fb5,0x3fed3fb5,0x3ff53fb5,0x3fe23fb5,0x3f153fb5,0xbf713fb5,0x3fc63ffb,0xbfffbec8,0xbfa2bec8,0xbe49bffb,
0xbe493f44,0x3fc6bf44,0xbfffbfed,0x3fa23fed,0xbfe2bf8e,0xbf153fd5,0xbf71bfd5,0xbff5bf8e,0xbf8e0000,0xbffb0000,0xbfd5c000,0xbec8c000,
0xbffbbfed,0x3fd5bf44,0x3ec8bf44,0x3f8e3fed,0xbec8bfb5,0xbf8e3fb5,0x3ffb3fb5,0xbfd5bfb5,0x3fd53f44,0x3ec8bfed,0x3f8e3fed,0x3ffb3f44,
0xbe49bfb5,0x3fa2bfb5,0x3fff3fb5,0x3fc63fb5,0x3ff53f8e,0xbf713fd5,0x3f153fd5,0xbfe2bf8e,0x3f713fed,0x3f15bfed,0xbfe2bf44,0x3ff53f44,
0xbfc6bec8,0xbe493ffb,0xbfa2bffb,0xbfffbec8,0x4000,0xbfb54000,0xc0000000,0xbfb50000,0xc000,0x3fb50000,0x40000000,0xbfb54000,
0x4000,0x3fb5c000,0xc0000000,0x3fb50000,0xc000,0xbfb50000,0x40000000,0x3fb5c000,0xbfa2bfb5,0x3e49bfb5,0x3fc6bfb5,0x3fffbfb5,
0x3f713fd5,0xbff53f8e,0xbfe23f8e,0x3f15bfd5,0xbf15bfed,0xbf713fed,0x3ff5bf44,0xbfe23f44,0x3e493ffb,0x3fc6bec8,0xbfff3ec8,0xbfa23ffb,
0x3ffb0000,0x3f8e0000,0xbec84000,0xbfd54000,0xbfd5bf44,0x3ffbbfed,0x3f8ebfed,0x3ec83f44,0x3f8e3fb5,0x3ec8bfb5,0xbfd53fb5,0x3ffbbfb5,
0xbec8bfed,0xbfd53f44,0x3ffbbf44,0x3f8ebfed,0xbfe23fb5,0xbff53fb5,0xbf71bfb5,0x3f15bfb5,0x3fffbec8,0xbfc63ffb,0xbe493ffb,0xbfa23ec8,
0xbfc6bf44,0x3e493f44,0x3fa2bfed,0xbfff3fed,0x3f153fd5,0x3fe2bf8e,0xbff53f8e,0xbf713fd5,0x3f44c000,0x3fedc000,0x3fed0000,0x3f440000,
0xbfed3fb5,0x3f44bfb5,0xbf44bfb5,0x3fedbfb5,0x3fed0000,0xbf440000,0xbf444000,0x3fedc000,0xbf44bfb5,0xbfed3fb5,0x3fedbfb5,0x3f44bfb5,
0x3f153fb5,0xbf713fb5,0xbff53fb5,0xbfe23fb5,0x3fa2bffb,0x3e493ec8,0x3fc63ec8,0xbfff3ffb,0xbfff3f44,0x3fa2bf44,0x3e49bfed,0xbfc63fed,
0x3f713f8e,0x3ff5bfd5,0xbfe23fd5,0xbf153f8e,0xbfd50000,0xbec80000,0x3f8ec000,0x3ffbc000,0xbec83fed,0xbf8e3f44,0xbffb3f44,0x3fd5bfed,
0x3ffbbfb5,0xbfd53fb5,0x3ec83fb5,0x3f8ebfb5,0xbf8ebf44,0xbffb3fed,0x3fd5bfed,0x3ec8bf44,0x3fffbfb5,0x3fc6bfb5,0x3e493fb5,0xbfa23fb5,
0xbf15bf8e,0x3fe2bfd5,0x3ff5bfd5,0xbf713f8e,0xbfe23fed,0x3ff5bfed,0xbf71bf44,0xbf153f44,0x3fa23ec8,0x3fffbffb,0xbfc63ffb,0xbe493ec8,
0xc0004000,0xbfb54000,0x0,0x3fb50000,0xc0004000,0x3fb50000,0x0,0x3fb5c000,0xc0004000,0x3fb5c000,0x0,0xbfb50000,
0xc0004000,0xbfb50000,0x0,0xbfb54000,0x3fc6bfb5,0x3fffbfb5,0x3fa2bfb5,0xbe49bfb5,0x3fe2bfd5,0xbf15bf8e,0x3f71bf8e,0xbff53fd5,
0x3ff5bfed,0xbfe23fed,0x3f15bf44,0x3f713f44,0x3fffbffb,0x3fa23ec8,0x3e49bec8,0x3fc6bffb,0xbec80000,0xbfd50000,0xbffb4000,0xbf8e4000,
0xbf8e3f44,0xbec83fed,0xbfd53fed,0x3ffbbf44,0xbfd53fb5,0x3ffbbfb5,0xbf8e3fb5,0xbec8bfb5,0xbffb3fed,0xbf8ebf44,0xbec83f44,0xbfd53fed,
0xbf713fb5,0x3f153fb5,0x3fe2bfb5,0x3ff5bfb5,0x3e493ec8,0x3fa2bffb,0x3fffbffb,0xbfc6bec8,0x3fa2bf44,0xbfff3f44,0x3fc6bfed,0xbe493fed,
0x3ff5bfd5,0x3f713f8e,0x3f15bf8e,0x3fe2bfd5,0x3fedc000,0x3f44c000,0xbf440000,0xbfed0000,0x3f44bfb5,0xbfed3fb5,0xbfed3fb5,0x3f443fb5,
0xbf440000,0x3fed0000,0xbfed4000,0x3f44c000,0xbfed3fb5,0xbf44bfb5,0xbf443fb5,0xbfed3fb5,0xbff53fb5,0xbfe23fb5,0xbf153fb5,0x3f713fb5,
0xbfc63ffb,0x3fffbec8,0x3fa2bec8,0x3e49bffb,0x3e493f44,0xbfc6bf44,0x3fffbfed,0xbfa23fed,0x3fe2bf8e,0x3f153fd5,0x3f71bfd5,0x3ff5bf8e,
0x3f8e0000,0x3ffb0000,0x3fd5c000,0x3ec8c000,0x3ffbbfed,0xbfd5bf44,0xbec8bf44,0xbf8e3fed,0x3ec8bfb5,0x3f8e3fb5,0xbffb3fb5,0x3fd5bfb5,
0xbfd53f44,0xbec8bfed,0xbf8e3fed,0xbffb3f44,0x3e49bfb5,0xbfa2bfb5,0xbfff3fb5,0xbfc63fb5,0xbff53f8e,0x3f713fd5,0xbf153fd5,0x3fe2bf8e,
0xbf713fed,0xbf15bfed,0x3fe2bf44,0xbff53f44,0x3fc6bec8,0x3e493ffb,0x3fa2bffb,0x3fffbec8,0x4000,0x3fb54000,0x40000000,0x3fb50000,
0xc000,0xbfb50000,0xc0000000,0x3fb54000,0x4000,0xbfb5c000,0x40000000,0xbfb50000,0xc000,0x3fb50000,0xc0000000,0xbfb5c000,
0x3fa2bfb5,0xbe49bfb5,0xbfc6bfb5,0xbfffbfb5,0xbf713fd5,0x3ff53f8e,0x3fe23f8e,0xbf15bfd5,0x3f15bfed,0x3f713fed,0xbff5bf44,0x3fe23f44,
0xbe493ffb,0xbfc6bec8,0x3fff3ec8,0x3fa23ffb,0xbffb0000,0xbf8e0000,0x3ec84000,0x3fd54000,0x3fd5bf44,0xbffbbfed,0xbf8ebfed,0xbec83f44,
0xbf8e3fb5,0xbec8bfb5,0x3fd53fb5,0xbffbbfb5,0x3ec8bfed,0x3fd53f44,0xbffbbf44,0xbf8ebfed,0x3fe23fb5,0x3ff53fb5,0x3f71bfb5,0xbf15bfb5,
0xbfffbec8,0x3fc63ffb,0x3e493ffb,0x3fa23ec8,0x3fc6bf44,0xbe493f44,0xbfa2bfed,0x3fff3fed,0xbf153fd5,0xbfe2bf8e,0x3ff53f8e,0x3f713fd5,
0xbf44c000,0xbfedc000,0xbfed0000,0xbf440000,0x3fed3fb5,0xbf44bfb5,0x3f44bfb5,0xbfedbfb5,0xbfed0000,0x3f440000,0x3f444000,0xbfedc000,
0x3f44bfb5,0x3fed3fb5,0xbfedbfb5,0xbf44bfb5,0xbf153fb5,0x3f713fb5,0x3ff53fb5,0x3fe23fb5,0xbfa2bffb,0xbe493ec8,0xbfc63ec8,0x3fff3ffb,
0x3fff3f44,0xbfa2bf44,0xbe49bfed,0x3fc63fed,0xbf713f8e,0xbff5bfd5,0x3fe23fd5,0x3f153f8e,0x3fd50000,0x3ec80000,0xbf8ec000,0xbffbc000,
0x3ec83fed,0x3f8e3f44,0x3ffb3f44,0xbfd5bfed,0xbffbbfb5,0x3fd53fb5,0xbec83fb5,0xbf8ebfb5,0x3f8ebf44,0x3ffb3fed,0xbfd5bfed,0xbec8bf44,
0xbfffbfb5,0xbfc6bfb5,0xbe493fb5,0x3fa23fb5,0x3f15bf8e,0xbfe2bfd5,0xbff5bfd5,0x3f713f8e,0x3fe23fed,0xbff5bfed,0x3f71bf44,0x3f153f44,
0xbfa23ec8,0xbfffbffb,0x3fc63ffb,0x3e493ec8,0x80003f80,0x3f800000,0x80003f80,0x3f800000,0x80003f80,0x3f800000,0x80003f80,0x3f800000,
0x80003f80,0x3f800000,0x80003f80,0x3f800000,0x80003f80,0x3f800000,0x80003f80,0x3f800000,0x80003f80,0x3f800000,0x8000bf80,0xbf800000,
0x3f353f35,0x3f35bf35,0xbf35bf35,0xbf353f35,0x3f800000,0xbf80,0xbf800000,0x3f80,0x3f35bf35,0xbf35bf35,0xbf353f35,0x3f353f35,
0x80003f80,0x3f800000,0x80003f80,0x3f800000,0x3f800000,0xbf80,0x3f800000,0xbf80,0x8000bf80,0xbf800000,0x8000bf80,0xbf800000,
0xbf800000,0x3f80,0xbf800000,0x3f80,0x80003f80,0x3f800000,0x8000bf80,0xbf800000,0x3f35bf35,0xbf35bf35,0xbf353f35,0x3f353f35,
0xbf800000,0x3f80,0x3f800000,0xbf80,0x3f353f35,0x3f35bf35,0xbf35bf35,0xbf353f35,0x80003f80,0x3f800000,0x80003f80,0x3f800000,
0x8000bf80,0xbf800000,0x8000bf80,0xbf800000,0x80003f80,0x3f800000,0x80003f80,0x3f800000,0x8000bf80,0xbf800000,0x8000bf80,0xbf800000,
0x80003f80,0x3f800000,0x8000bf80,0xbf800000,0xbf35bf35,0xbf353f35,0x3f353f35,0x3f35bf35,0x3f800000,0xbf80,0xbf800000,0x3f80,
0xbf353f35,0x3f353f35,0x3f35bf35,0xbf35bf35,0x80003f80,0x3f800000,0x80003f80,0x3f800000,0xbf800000,0x3f80,0xbf800000,0x3f80,
0x8000bf80,0xbf800000,0x8000bf80,0xbf800000,0x3f800000,0xbf80,0x3f800000,0xbf80,0x80003f80,0x3f800000,0x8000bf80,0xbf800000,
0xbf353f35,0x3f353f35,0x3f35bf35,0xbf35bf35,0xbf800000,0x3f80,0x3f800000,0xbf80,0xbf35bf35,0xbf353f35,0x3f353f35,0x3f35bf35,
0x3f803f80,0x80008000,0x80008000,0xbf80bf80,0x3f803f80,0x80008000,0x80008000,0xbf80bf80,0x3f803f80,0x80008000,0x80008000,0xbf80bf80,
0x3f803f80,0x80008000,0x80008000,0xbf80bf80,0x3f353f80,0x3f358000,0x3f358000,0xbf35bf80,0xbf350000,0x3f353f80,0x3f353f80,0x3f358000,
0xbf35bf80,0xbf358000,0xbf358000,0x3f353f80,0x3f350000,0xbf35bf80,0xbf35bf80,0xbf358000,0x3f80,0x3f808000,0x3f808000,0x8000bf80,
0xbf80,0xbf808000,0xbf808000,0x80003f80,0x3f80,0x3f808000,0x3f808000,0x8000bf80,0xbf80,0xbf808000,0xbf808000,0x80003f80,
0xbf353f80,0x3f358000,0x3f358000,0x3f35bf80,0x3f350000,0x3f35bf80,0x3f35bf80,0xbf358000,0x3f35bf80,0xbf358000,0xbf358000,0xbf353f80,
0xbf350000,0xbf353f80,0xbf353f80,0x3f358000,0xbf803f80,0x80008000,0x80008000,0x3f80bf80,0xbf803f80,0x80008000,0x80008000,0x3f80bf80,
0xbf803f80,0x80008000,0x80008000,0x3f80bf80,0xbf803f80,0x80008000,0x80008000,0x3f80bf80,0xbf353f80,0xbf358000,0xbf358000,0x3f35bf80,
0x3f350000,0xbf353f80,0xbf353f80,0xbf358000,0x3f35bf80,0x3f358000,0x3f358000,0xbf353f80,0xbf350000,0x3f35bf80,0x3f35bf80,0x3f358000,
0x3f80,0xbf808000,0xbf808000,0x8000bf80,0xbf80,0x3f808000,0x3f808000,0x80003f80,0x3f80,0xbf808000,0xbf808000,0x8000bf80,
0xbf80,0x3f808000,0x3f808000,0x80003f80,0x3f353f80,0xbf358000,0xbf358000,0xbf35bf80,0xbf350000,0xbf35bf80,0xbf35bf80,0x3f358000,
0xbf35bf80,0x3f358000,0x3f358000,0x3f353f80,0x3f350000,0x3f353f80,0x3f353f80,0xbf358000,0x3f800000,0x0,0x3f800000,0x0,
0x3f800000,0x0,0x3f800000,0x0,0x3f800000,0x0,0x3f800000,0x0,0x3f800000,0x0,0x3f800000,0x0,
0x3f800000,0x0,0x3f7fb10f,0xbd48fb30,0x3f7ec46d,0xbdc8bd36,0x3f7d3aac,0xbe164083,0x3f7b14be,0xbe47c5c2,0x3f7853f8,0xbe78cfcc,
0x3f74fa0b,0xbe94a031,0x3f710908,0xbeac7cd4,0x3f800000,0x0,0x3f7ec46d,0xbdc8bd36,0x3f7b14be,0xbe47c5c2,0x3f74fa0b,0xbe94a031,
0x3f6c835e,0xbec3ef15,0x3f61c598,0xbef15aea,0x3f54db31,0xbf0e39da,0x3f45e403,0xbf226799,0x3f800000,0x0,0x3f7d3aac,0xbe164083,
0x3f74fa0b,0xbe94a031,0x3f676bd8,0xbedae880,0x3f54db31,0xbf0e39da,0x3f3daef9,0xbf2beb4a,0x3f226799,0xbf45e403,0x3f039c3d,0xbf5b941a,
0x3f800000,0x0,0x3f7b14be,0xbe47c5c2,0x3f6c835e,0xbec3ef15,0x3f54db31,0xbf0e39da,0x3f3504f3,0xbf3504f3,0x3f0e39da,0xbf54db31,
0x3ec3ef15,0xbf6c835e,0x3e47c5c2,0xbf7b14be,0x3f800000,0x0,0x3f7853f8,0xbe78cfcc,0x3f61c598,0xbef15aea,0x3f3daef9,0xbf2beb4a,
0x3f0e39da,0xbf54db31,0x3eac7cd4,0xbf710908,0x3dc8bd36,0xbf7ec46d,0xbe164083,0xbf7d3aac,0x3f800000,0x0,0x3f74fa0b,0xbe94a031,
0x3f54db31,0xbf0e39da,0x3f226799,0xbf45e403,0x3ec3ef15,0xbf6c835e,0x3dc8bd36,0xbf7ec46d,0xbe47c5c2,0xbf7b14be,0xbef15aea,0xbf61c598,
0x3f800000,0x0,0x3f710908,0xbeac7cd4,0x3f45e403,0xbf226799,0x3f039c3d,0xbf5b941a,0x3e47c5c2,0xbf7b14be,0xbe164083,0xbf7d3aac,
0xbef15aea,0xbf61c598,0xbf3daef9,0xbf2beb4a,0x3f800000,0x0,0x3f800000,0x0,0x3f800000,0x0,0x3f800000,0x0,
0x3f800000,0x0,0x3f800000,0x0,0x3f800000,0x0,0x3f800000,0x0,0x3f6c835e,0xbec3ef15,0x3f676bd8,0xbedae880,
0x3f61c598,0xbef15aea,0x3f5b941a,0xbf039c3d,0x3f54db31,0xbf0e39da,0x3f4d9f02,0xbf187fc0,0x3f45e403,0xbf226799,0x3f3daef9,0xbf2beb4a,
0x3f3504f3,0xbf3504f3,0x3f226799,0xbf45e403,0x3f0e39da,0xbf54db31,0x3ef15aea,0xbf61c598,0x3ec3ef15,0xbf6c835e,0x3e94a031,0xbf74fa0b,
0x3e47c5c2,0xbf7b14be,0x3dc8bd36,0xbf7ec46d,0x3ec3ef15,0xbf6c835e,0x3e78cfcc,0xbf7853f8,0x3dc8bd36,0xbf7ec46d,0xbd48fb30,0xbf7fb10f,
0xbe47c5c2,0xbf7b14be,0xbeac7cd4,0xbf710908,0xbef15aea,0xbf61c598,0xbf187fc0,0xbf4d9f02,0x0,0xbf800000,0xbe47c5c2,0xbf7b14be,
0xbec3ef15,0xbf6c835e,0xbf0e39da,0xbf54db31,0xbf3504f3,0xbf3504f3,0xbf54db31,0xbf0e39da,0xbf6c835e,0xbec3ef15,0xbf7b14be,0xbe47c5c2,
0xbec3ef15,0xbf6c835e,0xbf187fc0,0xbf4d9f02,0xbf45e403,0xbf226799,0xbf676bd8,0xbedae880,0xbf7b14be,0xbe47c5c2,0xbf7fb10f,0x3d48fb30,
0xbf74fa0b,0x3e94a031,0xbf5b941a,0x3f039c3d,0xbf3504f3,0xbf3504f3,0xbf61c598,0xbef15aea,0xbf7b14be,0xbe47c5c2,0xbf7ec46d,0x3dc8bd36,
0xbf6c835e,0x3ec3ef15,0xbf45e403,0x3f226799,0xbf0e39da,0x3f54db31,0xbe94a031,0x3f74fa0b,0xbf6c835e,0xbec3ef15,0xbf7fb10f,0xbd48fb30,
0xbf74fa0b,0x3e94a031,0xbf4d9f02,0x3f187fc0,0xbf0e39da,0x3f54db31,0xbe78cfcc,0x3f7853f8,0x3dc8bd36,0x3f7ec46d,0x3edae880,0x3f676bd8,
0x80003f80,0x3f800000,0x3f800000,0xbf80,0x3ec43f6d,0x3f6dbec4,0x3f6dbec4,0xbec4bf6d,0x3f353f35,0x3f35bf35,0x3f35bf35,0xbf35bf35,
0x3f6d3ec4,0x3ec4bf6d,0x3ec4bf6d,0xbf6dbec4,0x80003f80,0x3f800000,0xbf800000,0x3f80,0x3f6d3ec4,0x3ec4bf6d,0xbec43f6d,0x3f6d3ec4,
0x3f35bf35,0xbf35bf35,0x3f353f35,0x3f35bf35,0xbec4bf6d,0xbf6d3ec4,0x3f6dbec4,0xbec4bf6d,0x80003f80,0x3f800000,0x3f800000,0xbf80,
0x3f6dbec4,0xbec4bf6d,0xbec4bf6d,0xbf6d3ec4,0xbf35bf35,0xbf353f35,0xbf353f35,0x3f353f35,0xbec43f6d,0x3f6d3ec4,0x3f6d3ec4,0x3ec4bf6d,
0x80003f80,0x3f800000,0xbf800000,0x3f80,0x3ec4bf6d,0xbf6dbec4,0x3f6d3ec4,0x3ec4bf6d,0xbf353f35,0x3f353f35,0xbf35bf35,0xbf353f35,
0x3f6dbec4,0xbec4bf6d,0x3ec43f6d,0x3f6dbec4,0x80003f80,0x3f800000,0x3f800000,0xbf80,0xbec4bf6d,0xbf6d3ec4,0xbf6d3ec4,0x3ec43f6d,
0x3f353f35,0x3f35bf35,0x3f35bf35,0xbf35bf35,0xbf6dbec4,0xbec43f6d,0xbec43f6d,0x3f6d3ec4,0x80003f80,0x3f800000,0xbf800000,0x3f80,
0xbf6dbec4,0xbec43f6d,0x3ec4bf6d,0xbf6dbec4,0x3f35bf35,0xbf35bf35,0x3f353f35,0x3f35bf35,0x3ec43f6d,0x3f6dbec4,0xbf6d3ec4,0x3ec43f6d,
0x80003f80,0x3f800000,0x3f800000,0xbf80,0xbf6d3ec4,0x3ec43f6d,0x3ec43f6d,0x3f6dbec4,0xbf35bf35,0xbf353f35,0xbf353f35,0x3f353f35,
0x3ec4bf6d,0xbf6dbec4,0xbf6dbec4,0xbec43f6d,0x80003f80,0x3f800000,0xbf800000,0x3f80,0xbec43f6d,0x3f6d3ec4,0xbf6dbec4,0xbec43f6d,
0xbf353f35,0x3f353f35,0xbf35bf35,0xbf353f35,0xbf6d3ec4,0x3ec43f6d,0xbec4bf6d,0xbf6d3ec4,0x3f803f80,0x80008000,0x80008000,0xbf80bf80,
0x3f803f80,0x80008000,0x80008000,0xbf80bf80,0x3f803f80,0x80008000,0x80008000,0xbf80bf80,0x3f803f80,0x80008000,0x80008000,0xbf80bf80,
0x3ec43f6d,0x3f6d3ec4,0x3f6d3ec4,0xbec4bf6d,0xbf6dbec4,0x3ec43f6d,0x3ec43f6d,0x3f6d3ec4,0xbec4bf6d,0xbf6dbec4,0xbf6dbec4,0x3ec43f6d,
0x3f6d3ec4,0xbec4bf6d,0xbec4bf6d,0xbf6dbec4,0xbf353f35,0x3f353f35,0x3f353f35,0x3f35bf35,0x3f35bf35,0xbf35bf35,0xbf35bf35,0xbf353f35,
0xbf353f35,0x3f353f35,0x3f353f35,0x3f35bf35,0x3f35bf35,0xbf35bf35,0xbf35bf35,0xbf353f35,0xbf6d3ec4,0xbec43f6d,0xbec43f6d,0x3f6dbec4,
0xbec43f6d,0x3f6dbec4,0x3f6dbec4,0x3ec4bf6d,0x3f6dbec4,0x3ec4bf6d,0x3ec4bf6d,0xbf6d3ec4,0x3ec4bf6d,0xbf6d3ec4,0xbf6d3ec4,0xbec43f6d,
0x0,0xbf803f80,0xbf803f80,0x80008000,0x0,0xbf803f80,0xbf803f80,0x80008000,0x0,0xbf803f80,0xbf803f80,0x80008000,
0x0,0xbf803f80,0xbf803f80,0x80008000,0x3f6dbec4,0xbec43f6d,0xbec43f6d,0xbf6d3ec4,0x3ec4bf6d,0x3f6dbec4,0x3f6dbec4,0xbec43f6d,
0xbf6d3ec4,0x3ec4bf6d,0x3ec4bf6d,0x3f6dbec4,0xbec43f6d,0xbf6d3ec4,0xbf6d3ec4,0x3ec4bf6d,0x3f35bf35,0x3f353f35,0x3f353f35,0xbf353f35,
0xbf353f35,0xbf35bf35,0xbf35bf35,0x3f35bf35,0x3f35bf35,0x3f353f35,0x3f353f35,0xbf353f35,0xbf353f35,0xbf35bf35,0xbf35bf35,0x3f35bf35,
0xbec4bf6d,0x3f6d3ec4,0x3f6d3ec4,0x3ec43f6d,0x3f6d3ec4,0x3ec43f6d,0x3ec43f6d,0xbf6dbec4,0x3ec43f6d,0xbf6dbec4,0xbf6dbec4,0xbec4bf6d,
0xbf6dbec4,0xbec4bf6d,0xbec4bf6d,0x3f6d3ec4,0x3f800000,0x0,0x3f7fec43,0xbcc90ab0,0x3f7fb10f,0xbd48fb30,0x3f7f4e6d,0xbd96a905,
0x3f7ec46d,0xbdc8bd36,0x3f7e1324,0xbdfab273,0x3f7d3aac,0xbe164083,0x3f7c3b28,0xbe2f10a2,0x3f800000,0x0,0x3f7f4e6d,0xbd96a905,
0x3f7d3aac,0xbe164083,0x3f79c79d,0xbe605c13,0x3f74fa0b,0xbe94a031,0x3f6ed89e,0xbeb8442a,0x3f676bd8,0xbedae880,0x3f5ebe05,0xbefc5d27,
0x3f800000,0x0,0x3f7e1324,0xbdfab273,0x3f7853f8,0xbe78cfcc,0x3f6ed89e,0xbeb8442a,0x3f61c598,0xbef15aea,0x3f514d3d,0xbf13682a,
0x3f3daef9,0xbf2beb4a,0x3f273656,0xbf41d870,0x3f800000,0x0,0x3f7c3b28,0xbe2f10a2,0x3f710908,0xbeac7cd4,0x3f5ebe05,0xbefc5d27,
0x3f45e403,0xbf226799,0x3f273656,0xbf41d870,0x3f039c3d,0xbf5b941a,0x3eb8442a,0xbf6ed89e,0x3f800000,0x0,0x3f79c79d,0xbe605c13,
0x3f676bd8,0xbedae880,0x3f49d112,0xbf1d7fd1,0x3f226799,0xbf45e403,0x3ee63375,0xbf64aa59,0x3e78cfcc,0xbf7853f8,0x3cc90ab0,0xbf7fec43,
0x3f800000,0x0,0x3f76ba07,0xbe888e93,0x3f5b941a,0xbf039c3d,0x3f3085bb,0xbf396842,0x3ef15aea,0xbf61c598,0x3e605c13,0xbf79c79d,
0xbd48fb30,0xbf7fb10f,0xbea09ae5,0xbf731447,0x3f800000,0x0,0x3f731447,0xbea09ae5,0x3f4d9f02,0xbf187fc0,0x3f13682a,0xbf514d3d,
0x3e94a031,0xbf74fa0b,0xbcc90ab0,0xbf7fec43,0xbeac7cd4,0xbf710908,0xbf1d7fd1,0xbf49d112,0x3f800000,0x0,0x3f6ed89e,0xbeb8442a,
0x3f3daef9,0xbf2beb4a,0x3ee63375,0xbf64aa59,0x3dc8bd36,0xbf7ec46d,0xbe888e93,0xbf76ba07,0xbf187fc0,0xbf4d9f02,0xbf584853,0xbf08f59b,
0x3f7b14be,0xbe47c5c2,0x3f79c79d,0xbe605c13,0x3f7853f8,0xbe78cfcc,0x3f76ba07,0xbe888e93,0x3f74fa0b,0xbe94a031,0x3f731447,0xbea09ae5,
0x3f710908,0xbeac7cd4,0x3f6ed89e,0xbeb8442a,0x3f54db31,0xbf0e39da,0x3f49d112,0xbf1d7fd1,0x3f3daef9,0xbf2beb4a,0x3f3085bb,0xbf396842,
0x3f226799,0xbf45e403,0x3f13682a,0xbf514d3d,0x3f039c3d,0xbf5b941a,0x3ee63375,0xbf64aa59,0x3f0e39da,0xbf54db31,0x3ee63375,0xbf64aa59,
0x3eac7cd4,0xbf710908,0x3e605c13,0xbf79c79d,0x3dc8bd36,0xbf7ec46d,0xbcc90ab0,0xbf7fec43,0xbe164083,0xbf7d3aac,0xbe888e93,0xbf76ba07,
0x3e47c5c2,0xbf7b14be,0x3cc90ab0,0xbf7fec43,0xbe164083,0xbf7d3aac,0xbea09ae5,0xbf731447,0xbef15aea,0xbf61c598,0xbf1d7fd1,0xbf49d112,
0xbf3daef9,0xbf2beb4a,0xbf584853,0xbf08f59b,0xbe47c5c2,0xbf7b14be,0xbecf7bca,0xbf6a09a7,0xbf187fc0,0xbf4d9f02,0xbf41d870,0xbf273656,
0xbf61c598,0xbef15aea,0xbf76ba07,0xbe888e93,0xbf7fb10f,0xbd48fb30,0xbf7c3b28,0x3e2f10a2,0xbf0e39da,0xbf54db31,0xbf41d870,0xbf273656,
0xbf676bd8,0xbedae880,0xbf7c3b28,0xbe2f10a2,0xbf7ec46d,0x3dc8bd36,0xbf6ed89e,0x3eb8442a,0xbf4d9f02,0x3f187fc0,0xbf1d7fd1,0x3f49d112,
0xbf54db31,0xbf0e39da,0xbf76ba07,0xbe888e93,0xbf7fb10f,0x3d48fb30,0xbf6ed89e,0x3eb8442a,0xbf45e403,0x3f226799,0xbf08f59b,0x3f584853,
0xbe78cfcc,0x3f7853f8,0x3d96a905,0x3f7f4e6d,0xbf7b14be,0xbe47c5c2,0xbf7c3b28,0x3e2f10a2,0xbf5b941a,0x3f039c3d,0xbf1d7fd1,0x3f49d112,
0xbe94a031,0x3f74fa0b,0x3d96a905,0x3f7f4e6d,0x3edae880,0x3f676bd8,0x3f396842,0x3f3085bb,0x80003f80,0x80003f80,0x80003f80,0x80003f80,
0x80003f80,0x80003f80,0x80003f80,0x80003f80,0x80003f80,0x80003f80,0x80003f80,0x80003f80,0x80003f80,0x80003f80,0x80003f80,0x80003f80,
0x3f800000,0x3f800000,0x3f800000,0x3f800000,0x3f800000,0x3f800000,0x3f800000,0x3f800000,0x3f800000,0x3f800000,0x3f800000,0x3f800000,
0x3f800000,0x3f800000,0x3f800000,0x3f800000,0x80003f80,0x3f353f35,0x80003f80,0x3f353f35,0x3f800000,0x3f35bf35,0x3f800000,0x3f35bf35,
0x8000bf80,0xbf35bf35,0x8000bf80,0xbf35bf35,0xbf800000,0xbf353f35,0xbf800000,0xbf353f35,0x3f800000,0x3f35bf35,0x3f800000,0x3f35bf35,
0xbf80,0xbf35bf35,0xbf80,0xbf35bf35,0xbf800000,0xbf353f35,0xbf800000,0xbf353f35,0x3f80,0x3f353f35,0x3f80,0x3f353f35,
0x80003f80,0x3f800000,0x80003f80,0x3f800000,0x8000bf80,0xbf800000,0x8000bf80,0xbf800000,0x80003f80,0x3f800000,0x80003f80,0x3f800000,
0x8000bf80,0xbf800000,0x8000bf80,0xbf800000,0x3f800000,0xbf80,0x3f800000,0xbf80,0xbf800000,0x3f80,0xbf800000,0x3f80,
0x3f800000,0xbf80,0x3f800000,0xbf80,0xbf800000,0x3f80,0xbf800000,0x3f80,0x80003f80,0x3f35bf35,0x80003f80,0x3f35bf35,
0xbf800000,0x3f353f35,0xbf800000,0x3f353f35,0x8000bf80,0xbf353f35,0x8000bf80,0xbf353f35,0x3f800000,0xbf35bf35,0x3f800000,0xbf35bf35,
0x3f800000,0xbf35bf35,0x3f800000,0xbf35bf35,0x3f80,0x3f35bf35,0x3f80,0x3f35bf35,0xbf800000,0x3f353f35,0xbf800000,0x3f353f35,
0xbf80,0xbf353f35,0xbf80,0xbf353f35,0x80003f80,0x3ec43f6d,0x8000bf80,0xbec4bf6d,0x3f353f35,0x3f6d3ec4,0xbf35bf35,0xbf6dbec4,
0x3f800000,0x3f6dbec4,0xbf800000,0xbf6d3ec4,0x3f35bf35,0x3ec4bf6d,0xbf353f35,0xbec43f6d,0x3f800000,0x3f6dbec4,0xbf800000,0xbf6d3ec4,
0x3f35bf35,0x3ec4bf6d,0xbf353f35,0xbec43f6d,0xbf80,0xbec4bf6d,0x3f80,0x3ec43f6d,0xbf35bf35,0xbf6dbec4,0x3f353f35,0x3f6d3ec4,
0x80003f80,0x3f6d3ec4,0x8000bf80,0xbf6dbec4,0x3f35bf35,0xbec4bf6d,0xbf353f35,0x3ec43f6d,0xbf800000,0xbec43f6d,0x3f800000,0x3ec4bf6d,
0x3f353f35,0x3f6dbec4,0xbf35bf35,0xbf6d3ec4,0x3f800000,0x3ec4bf6d,0xbf800000,0xbec43f6d,0xbf35bf35,0xbf6d3ec4,0x3f353f35,0x3f6dbec4,
0x3f80,0x3f6d3ec4,0xbf80,0xbf6dbec4,0x3f35bf35,0xbec4bf6d,0xbf353f35,0x3ec43f6d,0x80003f80,0x3f6dbec4,0x8000bf80,0xbf6d3ec4,
0xbf35bf35,0xbec43f6d,0x3f353f35,0x3ec4bf6d,0x3f800000,0xbec4bf6d,0xbf800000,0x3ec43f6d,0xbf353f35,0x3f6d3ec4,0x3f35bf35,0xbf6dbec4,
0x3f800000,0xbec4bf6d,0xbf800000,0x3ec43f6d,0xbf353f35,0x3f6d3ec4,0x3f35bf35,0xbf6dbec4,0xbf80,0xbf6d3ec4,0x3f80,0x3f6dbec4,
0x3f353f35,0x3ec4bf6d,0xbf35bf35,0xbec43f6d,0x80003f80,0x3ec4bf6d,0x8000bf80,0xbec43f6d,0xbf353f35,0x3f6dbec4,0x3f35bf35,0xbf6d3ec4,
0xbf800000,0x3f6d3ec4,0x3f800000,0xbf6dbec4,0xbf35bf35,0x3ec43f6d,0x3f353f35,0xbec4bf6d,0x3f800000,0xbf6dbec4,0xbf800000,0x3f6d3ec4,
0x3f353f35,0xbec4bf6d,0xbf35bf35,0x3ec43f6d,0x3f80,0x3ec4bf6d,0xbf80,0xbec43f6d,0xbf353f35,0x3f6dbec4,0x3f35bf35,0xbf6d3ec4,
0x80003f80,0x8000bf80,0x80003f80,0x8000bf80,0x80003f80,0x8000bf80,0x80003f80,0x8000bf80,0x80003f80,0x8000bf80,0x80003f80,0x8000bf80,
0x80003f80,0x8000bf80,0x80003f80,0x8000bf80,0x3f800000,0xbf800000,0x3f800000,0xbf800000,0x3f800000,0xbf800000,0x3f800000,0xbf800000,
0x3f800000,0xbf800000,0x3f800000,0xbf800000,0x3f800000,0xbf800000,0x3f800000,0xbf800000,0x80003f80,0xbf35bf35,0x80003f80,0xbf35bf35,
0x3f800000,0xbf353f35,0x3f800000,0xbf353f35,0x8000bf80,0x3f353f35,0x8000bf80,0x3f353f35,0xbf800000,0x3f35bf35,0xbf800000,0x3f35bf35,
0x3f800000,0xbf353f35,0x3f800000,0xbf353f35,0xbf80,0x3f353f35,0xbf80,0x3f353f35,0xbf800000,0x3f35bf35,0xbf800000,0x3f35bf35,
0x3f80,0xbf35bf35,0x3f80,0xbf35bf35,0x80003f80,0xbf800000,0x80003f80,0xbf800000,0x8000bf80,0x3f800000,0x8000bf80,0x3f800000,
0x80003f80,0xbf800000,0x80003f80,0xbf800000,0x8000bf80,0x3f800000,0x8000bf80,0x3f800000,0x3f800000,0x3f80,0x3f800000,0x3f80,
0xbf800000,0xbf80,0xbf800000,0xbf80,0x3f800000,0x3f80,0x3f800000,0x3f80,0xbf800000,0xbf80,0xbf800000,0xbf80,
0x80003f80,0xbf353f35,0x80003f80,0xbf353f35,0xbf800000,0xbf35bf35,0xbf800000,0xbf35bf35,0x8000bf80,0x3f35bf35,0x8000bf80,0x3f35bf35,
0x3f800000,0x3f353f35,0x3f800000,0x3f353f35,0x3f800000,0x3f353f35,0x3f800000,0x3f353f35,0x3f80,0xbf353f35,0x3f80,0xbf353f35,
0xbf800000,0xbf35bf35,0xbf800000,0xbf35bf35,0xbf80,0x3f35bf35,0xbf80,0x3f35bf35,0x80003f80,0xbec4bf6d,0x8000bf80,0x3ec43f6d,
0x3f353f35,0xbf6dbec4,0xbf35bf35,0x3f6d3ec4,0x3f800000,0xbf6d3ec4,0xbf800000,0x3f6dbec4,0x3f35bf35,0xbec43f6d,0xbf353f35,0x3ec4bf6d,
0x3f800000,0xbf6d3ec4,0xbf800000,0x3f6dbec4,0x3f35bf35,0xbec43f6d,0xbf353f35,0x3ec4bf6d,0xbf80,0x3ec43f6d,0x3f80,0xbec4bf6d,
0xbf35bf35,0x3f6d3ec4,0x3f353f35,0xbf6dbec4,0x80003f80,0xbf6dbec4,0x8000bf80,0x3f6d3ec4,0x3f35bf35,0x3ec43f6d,0xbf353f35,0xbec4bf6d,
0xbf800000,0x3ec4bf6d,0x3f800000,0xbec43f6d,0x3f353f35,0xbf6d3ec4,0xbf35bf35,0x3f6dbec4,0x3f800000,0xbec43f6d,0xbf800000,0x3ec4bf6d,
0xbf35bf35,0x3f6dbec4,0x3f353f35,0xbf6d3ec4,0x3f80,0xbf6dbec4,0xbf80,0x3f6d3ec4,0x3f35bf35,0x3ec43f6d,0xbf353f35,0xbec4bf6d,
0x80003f80,0xbf6d3ec4,0x8000bf80,0x3f6dbec4,0xbf35bf35,0x3ec4bf6d,0x3f353f35,0xbec43f6d,0x3f800000,0x3ec43f6d,0xbf800000,0xbec4bf6d,
0xbf353f35,0xbf6dbec4,0x3f35bf35,0x3f6d3ec4,0x3f800000,0x3ec43f6d,0xbf800000,0xbec4bf6d,0xbf353f35,0xbf6dbec4,0x3f35bf35,0x3f6d3ec4,
0xbf80,0x3f6dbec4,0x3f80,0xbf6d3ec4,0x3f353f35,0xbec43f6d,0xbf35bf35,0x3ec4bf6d,0x80003f80,0xbec43f6d,0x8000bf80,0x3ec4bf6d,
0xbf353f35,0xbf6d3ec4,0x3f35bf35,0x3f6dbec4,0xbf800000,0xbf6dbec4,0x3f800000,0x3f6d3ec4,0xbf35bf35,0xbec4bf6d,0x3f353f35,0x3ec43f6d,
0x3f800000,0x3f6d3ec4,0xbf800000,0xbf6dbec4,0x3f353f35,0x3ec43f6d,0xbf35bf35,0xbec4bf6d,0x3f80,0xbec43f6d,0xbf80,0x3ec4bf6d,
0xbf353f35,0xbf6d3ec4,0x3f35bf35,0x3f6dbec4,
};
constexpr int TB_F = 0, TB_E = 512, TB_P2 = 1024;

enum { C_EP = 0, C_Z1 = 32, C_Z2 = 96, C_H3 = 128, C_U = 160, C_X = 256, C_TOTAL = 512 };
struct Scratch {
  unsigned cnt[C_TOTAL];
  uint32_t moda[8 * 2 * D_];
  uint32_t mod[4 * D_ + 256];
  uint32_t z1[120 * 5120];
  uint32_t z2[128 * 4800];
  uint32_t x1[S_ * D_ / 2];
  uint8_t h3[32 * 18 * 4096];
  uint8_t u[72 * D_ * 128];
  uint4 part[128 * 1152];
};
__device__ __align__(1024) Scratch g_s;

#define PF2 8
#define PF2K 16
#define HOLDA 5
#define GOAT 3
#define HOLD1 1
#define HW bulk_commit_wait
#define H3W 0
#define X1K 10
#define PEEK 1
#define H3G 1
#define PFF 2
#define WAITALL 0
#ifndef NV1
#define NV1 12
#endif
#ifndef NV2
#define NV2 16
#endif
#define NG1 2

#define FAILCNT(k) do {} while (0)
#define CK(k) do {} while (0)
#define CKX(k) do {} while (0)
#define TS(k) do {} while (0)
#define TSC(k) do {} while (0)
struct Maps { CUtensorMap z1, z2[2], w1a, w1b, h3[2], w2, x1, out, wf[4], wm; };
struct Params {
  const __nv_bfloat16 *x, *c, *wmod;
  Scratch* s;
  const uint4* tab;
  const __nv_bfloat16 *wr, *wi, *w1, *w2, *b1, *b2;
};

__device__ __forceinline__ uint32_t smem_u32(const void* p) { return (uint32_t)__cvta_generic_to_shared(p); }
__device__ __forceinline__ void mbar_init(uint32_t b, int c) { asm volatile("mbarrier.init.shared::cta.b64 [%0], %1;" ::"r"(b), "r"(c)); }
__device__ __forceinline__ void mbar_expect(uint32_t b, int bytes) { asm volatile("mbarrier.arrive.expect_tx.shared::cta.b64 _, [%0], %1;" ::"r"(b), "r"(bytes) : "memory"); }
__device__ __forceinline__ void mbar_arrive(uint32_t b) { asm volatile("mbarrier.arrive.shared::cta.b64 _, [%0];" ::"r"(b) : "memory"); }
#define MBAR_WAIT(SEM)                                                                                                         \
  asm volatile("{\n.reg .pred p;\n.reg .u32 it;\nmov.u32 it, 0;\nW:\nmbarrier.try_wait.parity" SEM ".shared::cta.b64 p, [%0], %1;\n" \
               "@p bra.uni D;\nadd.u32 it, it, 1;\nsetp.lt.u32 p, it, 0x400000;\n@p bra.uni W;\ntrap;\nD:\n}" ::"r"(b), "r"(ph) : "memory")
__device__ __forceinline__ void mbar_wait(uint32_t b, int ph) { MBAR_WAIT(""); }
__device__ __forceinline__ uint32_t mbar_test(uint32_t b, int ph) {
  uint32_t ok;
  asm volatile("{\n.reg .pred p;\nmbarrier.test_wait.parity.shared::cta.b64 p, [%1], %2;\nselp.u32 %0, 1, 0, p;\n}\n" : "=r"(ok) : "r"(b), "r"(ph) : "memory");
  return ok;
}
__device__ __forceinline__ void tma2d(uint32_t dst, const CUtensorMap* m, int c0, int c1, uint32_t bar) {
  asm volatile("cp.async.bulk.tensor.2d.shared::cluster.global.mbarrier::complete_tx::bytes [%0], [%1, {%3, %4}], [%2];" ::"r"(dst), "l"(m), "r"(bar), "r"(c0), "r"(c1) : "memory");
}
__device__ __forceinline__ uint64_t pol_ef() { uint64_t p; asm("createpolicy.fractional.L2::evict_first.b64 %0, 1.0;" : "=l"(p)); return p; }
__device__ __forceinline__ void tma3d_ef(uint32_t dst, const CUtensorMap* m, int c1, int c2, uint32_t bar) {
  asm volatile("cp.async.bulk.tensor.3d.shared::cluster.global.mbarrier::complete_tx::bytes.L2::cache_hint [%0], [%1, {%3, %4, %5}], [%2], %6;" ::"r"(dst), "l"(m), "r"(bar), "r"(0), "r"(c1), "r"(c2), "l"(pol_ef()) : "memory");
}
__device__ __forceinline__ void tma4d_ef(uint32_t dst, const CUtensorMap* m, int c1, int c2, int c3, uint32_t bar) {
  asm volatile("cp.async.bulk.tensor.4d.shared::cluster.global.mbarrier::complete_tx::bytes.L2::cache_hint [%0], [%1, {%3, %7, %4, %5}], [%2], %6;" ::"r"(dst), "l"(m), "r"(bar), "r"(0), "r"(c2), "r"(c3), "l"(pol_ef()), "r"(c1) : "memory");
}
__device__ __forceinline__ void bulk_ld(uint32_t dst, const void* src, int bytes, uint32_t bar) {
  asm volatile("cp.async.bulk.shared::cluster.global.mbarrier::complete_tx::bytes [%0], [%1], %2, [%3];" ::"r"(dst), "l"(src), "r"(bytes), "r"(bar) : "memory");
}
__device__ __forceinline__ void bulk_st(void* dst, uint32_t src, int bytes) {
  asm volatile("cp.async.bulk.global.shared::cta.bulk_group [%0], [%1], %2;" ::"l"(dst), "r"(src), "r"(bytes) : "memory");
}
__device__ __forceinline__ void tma_st2d(const CUtensorMap* m, uint32_t src, int c0, int c1) {
  asm volatile("cp.async.bulk.tensor.2d.global.shared::cta.bulk_group [%0, {%2, %3}], [%1];" ::"l"(m), "r"(src), "r"(c0), "r"(c1) : "memory");
}
__device__ __forceinline__ void tma_st3d(const CUtensorMap* m, uint32_t src, int c0, int c1, int c2) {
  asm volatile("cp.async.bulk.tensor.3d.global.shared::cta.bulk_group [%0, {%2, %3, %4}], [%1];" ::"l"(m), "r"(src), "r"(c0), "r"(c1), "r"(c2) : "memory");
}
__device__ __forceinline__ void bulk_commit_wait_read() {
  asm volatile("cp.async.bulk.commit_group;" ::: "memory");
  asm volatile("cp.async.bulk.wait_group.read 0;" ::: "memory");
}
__device__ __forceinline__ void bulk_commit_wait() {
  asm volatile("cp.async.bulk.commit_group;" ::: "memory");
  asm volatile("cp.async.bulk.wait_group 0;" ::: "memory");
}
__device__ __forceinline__ void prefetch_l2(const void* p, int bytes) {
  asm volatile("cp.async.bulk.prefetch.L2.global [%0], %1;" ::"l"(p), "r"(bytes) : "memory");
}
__device__ __forceinline__ void wg_fence() { asm volatile("wgmma.fence.sync.aligned;" ::: "memory"); }
__device__ __forceinline__ void wg_commit() { asm volatile("wgmma.commit_group.sync.aligned;" ::: "memory"); }
template <int N> __device__ __forceinline__ void wg_wait() { asm volatile("wgmma.wait_group.sync.aligned %0;" ::"n"(N) : "memory"); }
template <int N> __device__ __forceinline__ void reg_fence(float (&d)[N]) {
#pragma unroll
  for (int i = 0; i < N; i++) asm volatile("" : "+f"(d[i])::"memory");
}
__device__ __forceinline__ void fence_async_smem() { asm volatile("fence.proxy.async.shared::cta;" ::: "memory"); }
__device__ __forceinline__ void fence_async_glb() { asm volatile("fence.proxy.async.global;" ::: "memory"); }
__device__ __forceinline__ uint32_t ld_rlx(const void* p) { uint32_t v; asm volatile("ld.relaxed.gpu.global.b32 %0, [%1];" : "=r"(v) : "l"(p) : "memory"); return v; }
__device__ __forceinline__ uint2 ld_rlx2(const void* p) { uint2 v; asm volatile("ld.relaxed.gpu.global.v2.b32 {%0,%1}, [%2];" : "=r"(v.x), "=r"(v.y) : "l"(p) : "memory"); return v; }
__device__ __forceinline__ uint4 ld_rlx4(const void* p) { uint4 v; asm volatile("ld.relaxed.gpu.global.v4.b32 {%0,%1,%2,%3}, [%4];" : "=r"(v.x), "=r"(v.y), "=r"(v.z), "=r"(v.w) : "l"(p) : "memory"); return v; }
__device__ __forceinline__ uint32_t ld_nc(const void* p) { uint32_t v; asm volatile("ld.global.nc.L1::no_allocate.b32 %0, [%1];" : "=r"(v) : "l"(p) : "memory"); return v; }
__device__ __forceinline__ uint4 ld_nc4(const void* p) { uint4 v; asm volatile("ld.global.nc.v4.b32 {%0,%1,%2,%3}, [%4];" : "=r"(v.x), "=r"(v.y), "=r"(v.z), "=r"(v.w) : "l"(p) : "memory"); return v; }
__device__ __forceinline__ uint32_t lds(uint32_t a) { uint32_t v; asm volatile("ld.shared.b32 %0, [%1];" : "=r"(v) : "r"(a) : "memory"); return v; }
__device__ __forceinline__ uint2 lds2(uint32_t a) { uint2 v; asm volatile("ld.shared.v2.b32 {%0,%1}, [%2];" : "=r"(v.x), "=r"(v.y) : "r"(a) : "memory"); return v; }
__device__ __forceinline__ uint4 lds4(uint32_t a) { uint4 v; asm volatile("ld.shared.v4.b32 {%0,%1,%2,%3}, [%4];" : "=r"(v.x), "=r"(v.y), "=r"(v.z), "=r"(v.w) : "r"(a) : "memory"); return v; }
__device__ __forceinline__ float lds_bf(uint32_t a) { uint32_t v; asm volatile("ld.shared.u16 %0, [%1];" : "=r"(v) : "r"(a) : "memory"); return __uint_as_float(v << 16); }
__device__ __forceinline__ void sts(uint32_t a, uint32_t v) { asm volatile("st.shared.b32 [%0], %1;" ::"r"(a), "r"(v) : "memory"); }
__device__ __forceinline__ void sts2(uint32_t a, uint32_t v0, uint32_t v1) { asm volatile("st.shared.v2.b32 [%0], {%1,%2};" ::"r"(a), "r"(v0), "r"(v1) : "memory"); }
__device__ __forceinline__ void sts4(uint32_t a, uint32_t v0, uint32_t v1, uint32_t v2, uint32_t v3) { asm volatile("st.shared.v4.b32 [%0], {%1,%2,%3,%4};" ::"r"(a), "r"(v0), "r"(v1), "r"(v2), "r"(v3) : "memory"); }
__device__ __forceinline__ void bar_sync(int id, int n) { asm volatile("bar.sync %0, %1;" ::"r"(id), "r"(n) : "memory"); }
__device__ __forceinline__ void bar_arrive(int id, int n) { asm volatile("bar.arrive %0, %1;" ::"r"(id), "r"(n) : "memory"); }
__device__ __forceinline__ void red_add(unsigned* p, unsigned v) { asm volatile("red.relaxed.gpu.global.add.u32 [%0], %1;" ::"l"(p), "r"(v) : "memory"); }
__device__ __forceinline__ bool any(bool p) { return __any_sync(0xffffffffu, p); }
constexpr int SPIN_MAX = 1 << 20;
__device__ __forceinline__ void wait_cnt(const unsigned* p, unsigned target) {
  int it = 0;
  while (any((int)(ld_rlx(p) - target) < 0) && ++it < SPIN_MAX) {}
}
__device__ __forceinline__ uint32_t pack_bf16(float lo, float hi) { uint32_t r; asm("cvt.rn.bf16x2.f32 %0, %1, %2;" : "=r"(r) : "f"(hi), "f"(lo)); return r; }
__device__ __forceinline__ float bf_lo(uint32_t v) { return __uint_as_float(v << 16); }
__device__ __forceinline__ float bf_hi(uint32_t v) { return __uint_as_float(v & 0xffff0000u); }
__device__ __forceinline__ uint32_t hadd2(uint32_t a, uint32_t b) { uint32_t r; asm("add.rn.bf16x2 %0, %1, %2;" : "=r"(r) : "r"(a), "r"(b)); return r; }
__device__ __forceinline__ uint32_t hmul2(uint32_t a, uint32_t b) { uint32_t r; asm("mul.rn.bf16x2 %0, %1, %2;" : "=r"(r) : "r"(a), "r"(b)); return r; }
__device__ __forceinline__ uint32_t hfma2(uint32_t a, uint32_t b, uint32_t c) { uint32_t r; asm("fma.rn.bf16x2 %0, %1, %2, %3;" : "=r"(r) : "r"(a), "r"(b), "r"(c)); return r; }
__device__ __forceinline__ float rbf(float x) { uint32_t r; asm("cvt.rn.bf16x2.f32 %0, %1, %2;" : "=r"(r) : "f"(x), "f"(0.0f)); return __uint_as_float(r); }
__device__ __forceinline__ void stmatrix4(uint32_t a, uint32_t r0, uint32_t r1, uint32_t r2, uint32_t r3) {
  asm volatile("stmatrix.sync.aligned.m8n8.x4.shared.b16 [%0], {%1,%2,%3,%4};" ::"r"(a), "r"(r0), "r"(r1), "r"(r2), "r"(r3) : "memory");
}
__device__ __forceinline__ void stmatrix2(uint32_t a, uint32_t r0, uint32_t r1) {
  asm volatile("stmatrix.sync.aligned.m8n8.x2.shared.b16 [%0], {%1,%2};" ::"r"(a), "r"(r0), "r"(r1) : "memory");
}
__device__ __forceinline__ void stmatrix4t(uint32_t a, uint32_t r0, uint32_t r1, uint32_t r2, uint32_t r3) {
  asm volatile("stmatrix.sync.aligned.m8n8.x4.trans.shared.b16 [%0], {%1,%2,%3,%4};" ::"r"(a), "r"(r0), "r"(r1), "r"(r2), "r"(r3) : "memory");
}
__device__ __forceinline__ uint32_t movm(uint32_t a) { uint32_t r; asm("movmatrix.sync.aligned.m8n8.trans.b16 %0, %1;" : "=r"(r) : "r"(a)); return r; }
template <bool ACC> __device__ __forceinline__ void mma16(float* d, uint32_t a0, uint32_t a1, uint32_t a2, uint32_t a3, uint32_t b0, uint32_t b1) {
  if (ACC) asm("mma.sync.aligned.m16n8k16.row.col.f32.bf16.bf16.f32 {%0,%1,%2,%3}, {%4,%5,%6,%7}, {%8,%9}, {%0,%1,%2,%3};"
               : "+f"(d[0]), "+f"(d[1]), "+f"(d[2]), "+f"(d[3]) : "r"(a0), "r"(a1), "r"(a2), "r"(a3), "r"(b0), "r"(b1));
  else asm("mma.sync.aligned.m16n8k16.row.col.f32.bf16.bf16.f32 {%0,%1,%2,%3}, {%4,%5,%6,%7}, {%8,%9}, {%10,%10,%10,%10};"
           : "=f"(d[0]), "=f"(d[1]), "=f"(d[2]), "=f"(d[3]) : "r"(a0), "r"(a1), "r"(a2), "r"(a3), "r"(b0), "r"(b1), "f"(0.f));
}
__device__ __forceinline__ uint32_t pin(uint32_t v) { uint32_t r; asm volatile("shfl.sync.bfly.b32 %0, %1, 0, 31, 0xffffffff;" : "=r"(r) : "r"(v)); return r; }
template <class T> __device__ __forceinline__ T* pin(T* p) {
  const uint64_t a = reinterpret_cast<uint64_t>(p);
  return reinterpret_cast<T*>((uint64_t)pin((uint32_t)a) | ((uint64_t)pin((uint32_t)(a >> 32)) << 32));
}
__device__ __forceinline__ uint32_t upin(uint32_t v) { return __shfl_sync(0xffffffffu, v, 0); }
template <class T> __device__ __forceinline__ T* upin(T* p) {
  const uint64_t a = reinterpret_cast<uint64_t>(p);
  return reinterpret_cast<T*>((uint64_t)upin((uint32_t)a) | ((uint64_t)upin((uint32_t)(a >> 32)) << 32));
}
__device__ __forceinline__ bool elect() {
  uint32_t p;
  asm volatile("{\n.reg .pred P;\nelect.sync _|P, 0xffffffff;\nselp.u32 %0, 1, 0, P;\n}" : "=r"(p));
  return p;
}
__device__ __forceinline__ uint32_t set_tag(uint32_t w, uint32_t tag) { uint32_t r; asm("lop3.b32 %0, %1, 0xfffffffe, %2, 0xea;" : "=r"(r) : "r"(w), "r"(tag)); return r; }
__device__ __forceinline__ uint32_t and_or(uint32_t w, uint32_t a, uint32_t o) { uint32_t r; asm("lop3.b32 %0, %1, %2, %3, 0xea;" : "=r"(r) : "r"(w), "r"(a), "r"(o)); return r; }
__device__ __forceinline__ uint32_t or3(uint32_t a, uint32_t b, uint32_t c) { uint32_t r; asm("lop3.b32 %0, %1, %2, %3, 0xfe;" : "=r"(r) : "r"(a), "r"(b), "r"(c)); return r; }
__device__ __forceinline__ uint32_t diff2(uint32_t a, uint32_t b, uint32_t tag) { uint32_t r; asm("lop3.b32 %0, %1, %2, %3, 0x7e;" : "=r"(r) : "r"(a), "r"(b), "r"(tag)); return r; }
__device__ __forceinline__ float2 cmul(float2 a, float2 b) { return make_float2(a.x * b.x - a.y * b.y, a.x * b.y + a.y * b.x); }

template<int TB> __device__ __forceinline__ void wgmma_ss_160_0(float (&d)[96], uint32_t al, uint32_t ah, uint32_t bl, uint32_t bh) {
  asm volatile("{\n.reg .b64 da, db;\nmov.b64 da, {%80, %81};\nmov.b64 db, {%82, %83};\n"
    "wgmma.mma_async.sync.aligned.m64n160k16.f32.bf16.bf16 {%0,%1,%2,%3,%4,%5,%6,%7,%8,%9,%10,%11,%12,%13,%14,%15,%16,%17,%18,%19,%20,%21,%22,%23,%24,%25,%26,%27,%28,%29,%30,%31,%32,%33,%34,%35,%36,%37,%38,%39,%40,%41,%42,%43,%44,%45,%46,%47,%48,%49,%50,%51,%52,%53,%54,%55,%56,%57,%58,%59,%60,%61,%62,%63,%64,%65,%66,%67,%68,%69,%70,%71,%72,%73,%74,%75,%76,%77,%78,%79}, da, db, 1, 1, 1, 1, %84;\n}\n"
    : "+f"(d[0]),"+f"(d[1]),"+f"(d[2]),"+f"(d[3]),"+f"(d[4]),"+f"(d[5]),"+f"(d[6]),"+f"(d[7]),"+f"(d[8]),"+f"(d[9]),"+f"(d[10]),"+f"(d[11]),"+f"(d[12]),"+f"(d[13]),"+f"(d[14]),"+f"(d[15]),"+f"(d[16]),"+f"(d[17]),"+f"(d[18]),"+f"(d[19]),"+f"(d[20]),"+f"(d[21]),"+f"(d[22]),"+f"(d[23]),"+f"(d[24]),"+f"(d[25]),"+f"(d[26]),"+f"(d[27]),"+f"(d[28]),"+f"(d[29]),"+f"(d[30]),"+f"(d[31]),"+f"(d[32]),"+f"(d[33]),"+f"(d[34]),"+f"(d[35]),"+f"(d[36]),"+f"(d[37]),"+f"(d[38]),"+f"(d[39]),"+f"(d[40]),"+f"(d[41]),"+f"(d[42]),"+f"(d[43]),"+f"(d[44]),"+f"(d[45]),"+f"(d[46]),"+f"(d[47]),"+f"(d[48]),"+f"(d[49]),"+f"(d[50]),"+f"(d[51]),"+f"(d[52]),"+f"(d[53]),"+f"(d[54]),"+f"(d[55]),"+f"(d[56]),"+f"(d[57]),"+f"(d[58]),"+f"(d[59]),"+f"(d[60]),"+f"(d[61]),"+f"(d[62]),"+f"(d[63]),"+f"(d[64]),"+f"(d[65]),"+f"(d[66]),"+f"(d[67]),"+f"(d[68]),"+f"(d[69]),"+f"(d[70]),"+f"(d[71]),"+f"(d[72]),"+f"(d[73]),"+f"(d[74]),"+f"(d[75]),"+f"(d[76]),"+f"(d[77]),"+f"(d[78]),"+f"(d[79])
    : "r"(al), "r"(ah), "r"(bl), "r"(bh), "n"(TB));
}
template<int TB> __device__ __forceinline__ void wgmma_ss_144_0(float (&d)[96], uint32_t al, uint32_t ah, uint32_t bl, uint32_t bh) {
  asm volatile("{\n.reg .b64 da, db;\nmov.b64 da, {%72, %73};\nmov.b64 db, {%74, %75};\n"
    "wgmma.mma_async.sync.aligned.m64n144k16.f32.bf16.bf16 {%0,%1,%2,%3,%4,%5,%6,%7,%8,%9,%10,%11,%12,%13,%14,%15,%16,%17,%18,%19,%20,%21,%22,%23,%24,%25,%26,%27,%28,%29,%30,%31,%32,%33,%34,%35,%36,%37,%38,%39,%40,%41,%42,%43,%44,%45,%46,%47,%48,%49,%50,%51,%52,%53,%54,%55,%56,%57,%58,%59,%60,%61,%62,%63,%64,%65,%66,%67,%68,%69,%70,%71}, da, db, 1, 1, 1, 1, %76;\n}\n"
    : "+f"(d[0]),"+f"(d[1]),"+f"(d[2]),"+f"(d[3]),"+f"(d[4]),"+f"(d[5]),"+f"(d[6]),"+f"(d[7]),"+f"(d[8]),"+f"(d[9]),"+f"(d[10]),"+f"(d[11]),"+f"(d[12]),"+f"(d[13]),"+f"(d[14]),"+f"(d[15]),"+f"(d[16]),"+f"(d[17]),"+f"(d[18]),"+f"(d[19]),"+f"(d[20]),"+f"(d[21]),"+f"(d[22]),"+f"(d[23]),"+f"(d[24]),"+f"(d[25]),"+f"(d[26]),"+f"(d[27]),"+f"(d[28]),"+f"(d[29]),"+f"(d[30]),"+f"(d[31]),"+f"(d[32]),"+f"(d[33]),"+f"(d[34]),"+f"(d[35]),"+f"(d[36]),"+f"(d[37]),"+f"(d[38]),"+f"(d[39]),"+f"(d[40]),"+f"(d[41]),"+f"(d[42]),"+f"(d[43]),"+f"(d[44]),"+f"(d[45]),"+f"(d[46]),"+f"(d[47]),"+f"(d[48]),"+f"(d[49]),"+f"(d[50]),"+f"(d[51]),"+f"(d[52]),"+f"(d[53]),"+f"(d[54]),"+f"(d[55]),"+f"(d[56]),"+f"(d[57]),"+f"(d[58]),"+f"(d[59]),"+f"(d[60]),"+f"(d[61]),"+f"(d[62]),"+f"(d[63]),"+f"(d[64]),"+f"(d[65]),"+f"(d[66]),"+f"(d[67]),"+f"(d[68]),"+f"(d[69]),"+f"(d[70]),"+f"(d[71])
    : "r"(al), "r"(ah), "r"(bl), "r"(bh), "n"(TB));
}
template<int TB> __device__ __forceinline__ void wgmma_ss_96_0(float (&d)[96], uint32_t al, uint32_t ah, uint32_t bl, uint32_t bh) {
  asm volatile("{\n.reg .b64 da, db;\nmov.b64 da, {%48, %49};\nmov.b64 db, {%50, %51};\n"
    "wgmma.mma_async.sync.aligned.m64n96k16.f32.bf16.bf16 {%0,%1,%2,%3,%4,%5,%6,%7,%8,%9,%10,%11,%12,%13,%14,%15,%16,%17,%18,%19,%20,%21,%22,%23,%24,%25,%26,%27,%28,%29,%30,%31,%32,%33,%34,%35,%36,%37,%38,%39,%40,%41,%42,%43,%44,%45,%46,%47}, da, db, 1, 1, 1, 1, %52;\n}\n"
    : "+f"(d[0]),"+f"(d[1]),"+f"(d[2]),"+f"(d[3]),"+f"(d[4]),"+f"(d[5]),"+f"(d[6]),"+f"(d[7]),"+f"(d[8]),"+f"(d[9]),"+f"(d[10]),"+f"(d[11]),"+f"(d[12]),"+f"(d[13]),"+f"(d[14]),"+f"(d[15]),"+f"(d[16]),"+f"(d[17]),"+f"(d[18]),"+f"(d[19]),"+f"(d[20]),"+f"(d[21]),"+f"(d[22]),"+f"(d[23]),"+f"(d[24]),"+f"(d[25]),"+f"(d[26]),"+f"(d[27]),"+f"(d[28]),"+f"(d[29]),"+f"(d[30]),"+f"(d[31]),"+f"(d[32]),"+f"(d[33]),"+f"(d[34]),"+f"(d[35]),"+f"(d[36]),"+f"(d[37]),"+f"(d[38]),"+f"(d[39]),"+f"(d[40]),"+f"(d[41]),"+f"(d[42]),"+f"(d[43]),"+f"(d[44]),"+f"(d[45]),"+f"(d[46]),"+f"(d[47])
    : "r"(al), "r"(ah), "r"(bl), "r"(bh), "n"(TB));
}
template<int TB> __device__ __forceinline__ void wgmma_ss_96_48(float (&d)[96], uint32_t al, uint32_t ah, uint32_t bl, uint32_t bh) {
  asm volatile("{\n.reg .b64 da, db;\nmov.b64 da, {%48, %49};\nmov.b64 db, {%50, %51};\n"
    "wgmma.mma_async.sync.aligned.m64n96k16.f32.bf16.bf16 {%0,%1,%2,%3,%4,%5,%6,%7,%8,%9,%10,%11,%12,%13,%14,%15,%16,%17,%18,%19,%20,%21,%22,%23,%24,%25,%26,%27,%28,%29,%30,%31,%32,%33,%34,%35,%36,%37,%38,%39,%40,%41,%42,%43,%44,%45,%46,%47}, da, db, 1, 1, 1, 1, %52;\n}\n"
    : "+f"(d[48]),"+f"(d[49]),"+f"(d[50]),"+f"(d[51]),"+f"(d[52]),"+f"(d[53]),"+f"(d[54]),"+f"(d[55]),"+f"(d[56]),"+f"(d[57]),"+f"(d[58]),"+f"(d[59]),"+f"(d[60]),"+f"(d[61]),"+f"(d[62]),"+f"(d[63]),"+f"(d[64]),"+f"(d[65]),"+f"(d[66]),"+f"(d[67]),"+f"(d[68]),"+f"(d[69]),"+f"(d[70]),"+f"(d[71]),"+f"(d[72]),"+f"(d[73]),"+f"(d[74]),"+f"(d[75]),"+f"(d[76]),"+f"(d[77]),"+f"(d[78]),"+f"(d[79]),"+f"(d[80]),"+f"(d[81]),"+f"(d[82]),"+f"(d[83]),"+f"(d[84]),"+f"(d[85]),"+f"(d[86]),"+f"(d[87]),"+f"(d[88]),"+f"(d[89]),"+f"(d[90]),"+f"(d[91]),"+f"(d[92]),"+f"(d[93]),"+f"(d[94]),"+f"(d[95])
    : "r"(al), "r"(ah), "r"(bl), "r"(bh), "n"(TB));
}
__device__ __forceinline__ void wgmma_rs_72(float (&d)[36], uint32_t a0, uint32_t a1, uint32_t a2, uint32_t a3, uint32_t bl, uint32_t bh, int sd) {
  asm volatile("{\n.reg .pred p;\n.reg .b64 db;\nsetp.ne.b32 p, %42, 0;\nmov.b64 db, {%40, %41};\n"
    "wgmma.mma_async.sync.aligned.m64n72k16.f32.bf16.bf16 {%0,%1,%2,%3,%4,%5,%6,%7,%8,%9,%10,%11,%12,%13,%14,%15,%16,%17,%18,%19,%20,%21,%22,%23,%24,%25,%26,%27,%28,%29,%30,%31,%32,%33,%34,%35}, {%36,%37,%38,%39}, db, p, 1, 1, 1;\n}\n"
    : "+f"(d[0]),"+f"(d[1]),"+f"(d[2]),"+f"(d[3]),"+f"(d[4]),"+f"(d[5]),"+f"(d[6]),"+f"(d[7]),"+f"(d[8]),"+f"(d[9]),"+f"(d[10]),"+f"(d[11]),"+f"(d[12]),"+f"(d[13]),"+f"(d[14]),"+f"(d[15]),"+f"(d[16]),"+f"(d[17]),"+f"(d[18]),"+f"(d[19]),"+f"(d[20]),"+f"(d[21]),"+f"(d[22]),"+f"(d[23]),"+f"(d[24]),"+f"(d[25]),"+f"(d[26]),"+f"(d[27]),"+f"(d[28]),"+f"(d[29]),"+f"(d[30]),"+f"(d[31]),"+f"(d[32]),"+f"(d[33]),"+f"(d[34]),"+f"(d[35])
    : "r"(a0), "r"(a1), "r"(a2), "r"(a3), "r"(bl), "r"(bh), "r"(sd));
}
__device__ __forceinline__ void wgmma_rs_48(float (&d)[24], uint32_t a0, uint32_t a1, uint32_t a2, uint32_t a3, uint32_t bl, uint32_t bh, int sd) {
  asm volatile("{\n.reg .pred p;\n.reg .b64 db;\nsetp.ne.b32 p, %30, 0;\nmov.b64 db, {%28, %29};\n"
    "wgmma.mma_async.sync.aligned.m64n48k16.f32.bf16.bf16 {%0,%1,%2,%3,%4,%5,%6,%7,%8,%9,%10,%11,%12,%13,%14,%15,%16,%17,%18,%19,%20,%21,%22,%23}, {%24,%25,%26,%27}, db, p, 1, 1, 1;\n}\n"
    : "+f"(d[0]),"+f"(d[1]),"+f"(d[2]),"+f"(d[3]),"+f"(d[4]),"+f"(d[5]),"+f"(d[6]),"+f"(d[7]),"+f"(d[8]),"+f"(d[9]),"+f"(d[10]),"+f"(d[11]),"+f"(d[12]),"+f"(d[13]),"+f"(d[14]),"+f"(d[15]),"+f"(d[16]),"+f"(d[17]),"+f"(d[18]),"+f"(d[19]),"+f"(d[20]),"+f"(d[21]),"+f"(d[22]),"+f"(d[23])
    : "r"(a0), "r"(a1), "r"(a2), "r"(a3), "r"(bl), "r"(bh), "r"(sd));
}
template<int N,int OFF,int TB> __device__ __forceinline__ void wgmma_ss(float (&d)[96], uint32_t al, uint32_t ah, uint32_t bl, uint32_t bh) {
  if constexpr (N==160 && OFF==0) wgmma_ss_160_0<TB>(d, al, ah, bl, bh);
  else if constexpr (N==144 && OFF==0) wgmma_ss_144_0<TB>(d, al, ah, bl, bh);
  else if constexpr (N==96 && OFF==0) wgmma_ss_96_0<TB>(d, al, ah, bl, bh);
  else if constexpr (N==96 && OFF==48) wgmma_ss_96_48<TB>(d, al, ah, bl, bh);
}

__device__ __forceinline__ void dft3(float2& a, float2& b, float2& c) {
  const float s = 0.86602540378443864676f;
  float2 t = make_float2(b.x + c.x, b.y + c.y), d = make_float2(b.x - c.x, b.y - c.y);
  float2 m = make_float2(fmaf(-0.5f, t.x, a.x), fmaf(-0.5f, t.y, a.y));
  a = make_float2(a.x + t.x, a.y + t.y);
  b = make_float2(fmaf(s, d.y, m.x), fmaf(-s, d.x, m.y));
  c = make_float2(fmaf(-s, d.y, m.x), fmaf(s, d.x, m.y));
}
__device__ __forceinline__ void dft9(float2 (&x)[9]) {
  const float2 w1 = make_float2(0.76604444311897803520f, -0.64278760968653932632f);
  const float2 w2 = make_float2(0.17364817766693034885f, -0.98480775301220805937f);
  const float2 w4 = make_float2(-0.93969262078590838405f, -0.34202014332566873304f);
  dft3(x[0], x[3], x[6]); dft3(x[1], x[4], x[7]); dft3(x[2], x[5], x[8]);
  x[4] = cmul(x[4], w1); x[7] = cmul(x[7], w2); x[5] = cmul(x[5], w2); x[8] = cmul(x[8], w4);
  dft3(x[0], x[1], x[2]); dft3(x[3], x[4], x[5]); dft3(x[6], x[7], x[8]);
  float2 t;
  t = x[1]; x[1] = x[3]; x[3] = t;
  t = x[2]; x[2] = x[6]; x[6] = t;
  t = x[5]; x[5] = x[7]; x[7] = t;
}

__device__ __forceinline__ uint32_t* mod_ptr(Scratch* sc, int u, int t128) {
  const int i = t128 & 15;
  return u < 72 ? sc->moda + (t128 >> 4) * (2 * D_) + 16 * u + 2 * (i & 7) + (i >> 3) : sc->mod + 16 * (u - 72) + i;
}
__device__ __forceinline__ void mod_unit(Scratch* sc, int u, int t128, uint32_t sw_, uint32_t bar, int ph, uint32_t rb, uint32_t tag) {
  const int w = t128 >> 5, l = t128 & 31;
  uint32_t b[18];
#pragma unroll
  for (int i = 0; i < 18; i++) b[i] = lds(red + 512 + (72 * w + 4 * i + (l & 3)) * 4);
  const uint32_t sa = pin(sw_ + (144 * w + (l & 7) + 8 * (l >> 4)) * 32 + (((l >> 3) ^ (l >> 2)) & 1) * 16);
  const uint32_t sr = pin(rb + (l >> 2) * 16 + w * 4);
  uint32_t* const dst = pin(mod_ptr(sc, u, t128));
  const int kind = u / 36;
  const float mul = __uint_as_float(pin(__float_as_uint(kind == 0 ? 16.0f : 1.0f))), add = __uint_as_float(pin(__float_as_uint(kind == 1 || kind == 4 ? 1.0f : 0.0f)));
  mbar_wait(bar, ph);
  if (t128 == 0 && u < 72) TS(10);
  float d[3][4];
#pragma unroll
  for (int i = 0; i < 9; i++) {
    uint32_t a0, a1, a2, a3;
    asm volatile("ldmatrix.sync.aligned.m8n8.x4.trans.shared.b16 {%0,%1,%2,%3}, [%4];" : "=r"(a0), "=r"(a1), "=r"(a2), "=r"(a3) : "r"(sa + i * 512) : "memory");
    if (i < 3) mma16<false>(d[i], a0, a1, a2, a3, b[2 * i], b[2 * i + 1]);
    else mma16<true>(d[i % 3], a0, a1, a2, a3, b[2 * i], b[2 * i + 1]);
  }
  if ((l & 3) == 0) { sts(sr, __float_as_uint(d[0][0] + d[1][0] + d[2][0])); sts(sr + 128, __float_as_uint(d[0][2] + d[1][2] + d[2][2])); }
  bar_sync(4, 128);
  const uint4 v = lds4(rb + (l & 15) * 16);
  const float m = rbf(fmaf(rbf((__uint_as_float(v.x) + __uint_as_float(v.y)) + (__uint_as_float(v.z) + __uint_as_float(v.w))), mul, add));
  if (u < 72 || t128 < 16) *dst = __float_as_uint(m) | tag;
}

__device__ __forceinline__ float rsq(float x) { float r; asm("rsqrt.approx.ftz.f32 %0, %1;" : "=f"(r) : "f"(x)); return r; }
__device__ __forceinline__ void ln_stats2(const float (&a)[18], const float (&b)[18], float sc, float& oa, float& ra, float& ob, float& rb) {
  float v[4] = {0.f, 0.f, 0.f, 0.f}, w[4] = {0.f, 0.f, 0.f, 0.f};
#pragma unroll
  for (int i = 0; i < 18; i += 2) {
    v[0] += a[i]; v[1] = fmaf(a[i], a[i], v[1]); v[2] += b[i]; v[3] = fmaf(b[i], b[i], v[3]);
    w[0] += a[i + 1]; w[1] = fmaf(a[i + 1], a[i + 1], w[1]); w[2] += b[i + 1]; w[3] = fmaf(b[i + 1], b[i + 1], w[3]);
  }
#pragma unroll
  for (int e = 0; e < 4; e++) v[e] += w[e];
#pragma unroll
  for (int o = 16; o; o >>= 1) {
#pragma unroll
    for (int e = 0; e < 4; e++) v[e] += __shfl_xor_sync(0xffffffffu, v[e], o);
  }
  const float ma = v[0] * (1.0f / D_), mb = v[2] * (1.0f / D_);
  ra = sc * rsq(fmaxf(fmaf(-ma, ma, v[1] * (1.0f / D_)), 0.f) + 1e-5f);
  rb = sc * rsq(fmaxf(fmaf(-mb, mb, v[3] * (1.0f / D_)), 0.f) + 1e-5f);
  oa = -ma * ra; ob = -mb * rb;
}

__device__ __forceinline__ float tmat(int c, int q, int j) {
  const int ph = q == 1 ? 1024 * j : (q >> 1) * (c + 128 * j) + 512 * (q & 1);
  return __cosf((float)(((ph + 1024) & 2047) - 1024) * (6.283185307179586f / 2048.0f));
}
__device__ __forceinline__ uint32_t line_off(int k1, int kap, int pi, int f) {
  int kd = 64 * k1 + 9 * kap;
  if (kap == 0 && k1 > 4) kd -= 288;
  if (kd >= D_) kd -= D_;
  return pi * 2400 + ((min(kd, D_ - kd) ^ f) << 3);
}

constexpr int JSK = 5;
struct Ring { uint32_t st, ph; };
template <bool G2, class T> __device__ __forceinline__ void ring_next(T& st, T& ph) {
  st = ((G2 ? 0x054132u : 0x054321u) >> (4 * st)) & 7;
  ph ^= ((G2 ? 0x7u : 0x1u) >> st) & 1;
}
__device__ __forceinline__ void arrive_if(uint32_t a, uint32_t p) {
  asm volatile("{\n.reg .pred p;\nsetp.ne.u32 p, %1, 0;\n@p mbarrier.arrive.shared::cta.b64 _, [%0];\n}" ::"r"(a), "r"(p) : "memory");
}
template <int NA> __device__ __forceinline__ void reg_fence_n(float (&d)[96]) {
#pragma unroll
  for (int i = 0; i < NA; i++) asm volatile("" : "+f"(d[i])::"memory");
}
template <int MODE>
__device__ __forceinline__ void gemm_main(float (&acc)[96], uint32_t da0, uint32_t da1, uint32_t db0, int wg, Ring& rg,
                                          uint32_t* x1p, const uint32_t (&xr)[18]) {
  static_assert(JSK == NST - 1, "the held slot is the first one that is not refilled by GEMM1");
  constexpr int NKB = MODE == 3 ? 36 : 32;
  constexpr uint32_t HA = 0x40000040u, HB = MODE == 3 ? 0x40000040u : 0x80000020u;
  constexpr uint32_t KA = 2048 >> 4, KB = MODE == 3 ? (32 >> 4) : (1024 >> 4);
  constexpr int NA = MODE == 3 ? 72 : MODE == 1 ? 96 : 80;
  const uint32_t t = threadIdx.x & 127;
  const uint32_t eb = full0 + 8 * NST;
  uint32_t pb = 0, rel = t == 0, prel = 0, ok = 0;
  int n = MODE == 3 ? NKB - JSK : X1K + 2 * wg;
#pragma unroll 1
  for (int pass = MODE == 3 ? 0 : -1;; pass++) {
#pragma unroll 1
    do {
      const uint32_t so = rg.st * (STAGE >> 4), cb = eb + 8 * rg.st;
      if (__builtin_expect(!ok, 0)) mbar_wait(full0 + 8 * rg.st, rg.ph);
      reg_fence_n<NA>(acc);
      if (MODE == 1 && wg) {
        wg_fence();
#pragma unroll
        for (int k = 0; k < 4; k++) wgmma_ss<96, 48, 1>(acc, da1 + so + k * KA, HA, db0 + so + k * KB, HB);
        wg_commit();
      }
      wg_fence();
#pragma unroll
      for (int k = 0; k < 4; k++) {
        if (k == 3) { ring_next<MODE == 3>(rg.st, rg.ph); ok = PEEK ? mbar_test(full0 + 8 * rg.st, rg.ph) : 0; }
        if (MODE == 0) wgmma_ss<160, 0, 1>(acc, da0 + so + k * KA, HA, db0 + so + k * KB, HB);
        else if (MODE == 3) wgmma_ss<144, 0, 0>(acc, da0 + so + k * KA, HA, db0 + so + k * KB, HB);
        else wgmma_ss<96, 0, 1>(acc, da0 + so + k * KA, HA, db0 + so + k * KB, HB);
      }
      wg_commit();
      wg_wait<1>();
      reg_fence_n<NA>(acc);
      arrive_if(pb, prel);
      pb = cb; prel = rel;
    } while (--n);
    if (pass == 2 - wg) break;
    if (MODE != 3 && pass < 0) {
      if (blockIdx.x < 128) {
#pragma unroll
        for (int i = 0; i < 9; i++) { x1p[32 * i] = xr[i]; x1p[128 * 288 + 32 * i] = xr[9 + i]; }
      }
      n = NKB - JSK - X1K - 2 * wg;
      continue;
    }
    n = 1;
    if (pass == 0) {
      if (MODE != 3) prel = rel & wg;
      else rel = 0;
      n = JSK - 1 + wg;
      if (!wg) continue;
      wg_wait<0>();
      arrive_if(pb, prel);
      prel = 0;
    }
    bar_sync(1, 256);
  }
  wg_wait<0>();
  reg_fence_n<NA>(acc);
  if (MODE != 3) arrive_if(pb, prel & ~wg);
}

__device__ __forceinline__ float gelu_arg(float h) { return h * fmaf(8.0f * 0.044715f * 0.7978845608028654f, h * h, 2.0f * 0.7978845608028654f); }

__device__ __forceinline__ int kb2_order(int i) { const int wv = i / 6; return 6 * (i - 6 * wv) + ((0x431250 >> (4 * wv)) & 7); }

__device__ __forceinline__ void wait_flags(const unsigned* base, int n, int idx, unsigned target, uint64_t& ready) {
  if ((ready >> idx) & 1) return;
  const int l = threadIdx.x & 31;
  int it = 0;
  while (true) {
    unsigned a = ld_rlx(base + l), b = l + 32 < n ? ld_rlx(base + l + 32) : target;
    ready = (uint64_t)__ballot_sync(0xffffffffu, (int)(a - target) >= 0) | ((uint64_t)__ballot_sync(0xffffffffu, (int)(b - target) >= 0) << 32);
    if (((ready >> idx) & 1) || ++it > SPIN_MAX) break;
  }
}

enum { B_FULL = 0, B_EMPTY = 6, B_S4 = 12, B_S5, B_LAND, B_FLT = B_LAND + 6, B_Z1, B_Z2, B_GO, B_X, B_WM, B_NUM, B_W0 = B_NUM };

__global__ void __launch_bounds__(NTHR, 1)
fused_kernel(const Params p, const __grid_constant__ Maps maps) {
  extern __shared__ __align__(1024) uint8_t smem_raw[];
  const int tid = threadIdx.x, cta = blockIdx.x, t128 = tid & 127;
  const int wp = __shfl_sync(0xffffffffu, tid >> 5, 0), wg = wp >> 2;
  const int l = tid & 31, g = l >> 2, t = l & 3;
  Scratch* const sc = p.s;
  const bool rows = cta < 128;
  const int R = cta - 12;

  uint32_t xr[18];
  uint32_t cv[3];
  const unsigned ep = ld_rlx(&sc->cnt[C_EP]) + 1;
  if (tid == 0) TS(0);
  if (wg == 2) {
#pragma unroll
    for (int i = 0; i < 3; i++) cv[i] = ld_nc(reinterpret_cast<const uint32_t*>(p.c) + min(t128 + 128 * i, 287));
    if (wp == 9 && l < 9 && rows) {
      const int h = 9 * cta + l;
      prefetch_l2(reinterpret_cast<const uint8_t*>(p.wmod) + (size_t)(h >> 1) * (12 * D_) + (h & 1) * (2 * D_), 2 * D_);
    }
    if (tid == 256 && cta < 72) {
      mbar_init(full0 + 8 * B_W0, 1);
      fence_async_smem();
      mbar_expect(full0 + 8 * B_W0, 18432);
#pragma unroll 1
      for (int i = 0; i < 3; i++) tma2d(sbase + O_P2 + i * 6144, &maps.wm, 16 * cta, 192 * i, full0 + 8 * B_W0);
    }
    __syncwarp();
#pragma unroll 1
    for (int u = cta < 72 ? cta : 72 + cta; u < 216; u += u < 72 ? 72 : NCTA) if (u < 72 || t128 < 16) *mod_ptr(sc, u, t128) = 0;
    if (wp == 11 && smem_u32(smem_raw) != sbase) __trap();
    if (wp >= 10 && elect()) {
#pragma unroll 1
      for (int i = wp - 10; i < B_NUM; i += 2) mbar_init(full0 + 8 * i, i == B_FLT ? 4 : i == B_WM ? 3 : i < B_LAND ? 2 : 1);
      fence_async_smem();
    }
    __syncwarp();
  }
  CK(0);
  auto load_x = [&]() {
    const uint32_t* xs = reinterpret_cast<const uint32_t*>(p.x) + (size_t)(cta + 256 * wp) * 288 + l;
#pragma unroll
    for (int i = 0; i < 9; i++) { xr[i] = ld_nc(xs + 32 * i); xr[9 + i] = ld_nc(xs + 128 * 288 + 32 * i); }
  };
  if (rows && wg < 2) load_x();
  if (tid == 64 && cta == NCTA - 1) prefetch_l2(p.tab, sizeof(T_TAB));
  __syncwarp();
  const uint32_t tag16 = (ep & 0x7fffu) | 0x8000u, tag1 = ep & 1u;

  if (wg == 2) {
#pragma unroll
    for (int i = 0; i < 3; i++) {
      const float c0 = bf_lo(cv[i]), c1 = bf_hi(cv[i]);
      sts(red + 512 + min(t128 + 128 * i, 287) * 4, pack_bf16(__fdividef(c0, 1.0f + __expf(-c0)), __fdividef(c1, 1.0f + __expf(-c1))));
    }
    if (wp == 9 && l < 14) asm volatile("prefetch.tensormap [%0];" ::"l"(&maps.z1 + l) : "memory");
    bar_sync(4, 128);
    if (cta < 72) {
      mod_unit(sc, cta, t128, sbase + O_P2, full0 + 8 * B_W0, 0, red, tag16);
      if (t128 == 0) TS(25);
    }
    CK(1);
  }
  const int pi = R / 15, col0 = 20 * (R - 15 * pi);
  const int xu = DF_ * pi + col0, xv = DF_ * (pi ? 16 - pi : 8) + col0;
  auto load_filter = [&](int a) {
    const int x = (a & 1) ? xv : xu;
    const bool wide = (x & 15) > 12;
    mbar_expect(full0 + 8 * B_FLT, wide ? 12288 : 8192);
    tma2d(sbase + O_RAW + a * 12288, &maps.wf[a & 2], x & ~15, 0, full0 + 8 * B_FLT);
    if (wide) tma2d(sbase + O_RAW + a * 12288 + 8192, &maps.wf[(a & 2) + 1], (x & ~15) + 32, 0, full0 + 8 * B_FLT);
  };
  const int kap = 8 * ((wp & 3) ^ (wg & 1)) + g;
  uint4 af[4];
  if (rows) {
    uint32_t tb[4];
#pragma unroll
    for (int i = 0; i < 4; i++) tb[i] = pack_bf16(tmat(cta, 8 * (i >> 1) + g, 2 * t + 8 * (i & 1)), tmat(cta, 8 * (i >> 1) + g, 2 * t + 8 * (i & 1) + 1));
    uint32_t sb1[3], lo[9];
#pragma unroll
    for (int i = 0; i < 4; i++) tb[i] = pin(tb[i]);
#pragma unroll
    for (int i = 0; i < 3; i++) {
      const int d = 48 * wp + 16 * i + (l & 15);
      sb1[i] = pin(sbase + O_B1 + (l >> 4) * 9216 + (d % 9) * 1024 + (d & 63) * 16);
    }
    const uint32_t snt = pin(sbase + O_NRM + ((l & 7) + 8 * (l >> 4)) * 1168 + (48 * wp + (l & 8)) * 2);
    uint2 ms[3], mc[3];
    const uint32_t smask = pin(t ? 0u : 0xffff0000u);
    const uint32_t* const mp = pin(sc->moda + (cta >> 4) * (2 * D_) + 48 * wp + 2 * g);
    auto load_mod = [&]() {
#pragma unroll
      for (int i = 0; i < 3; i++) { ms[i] = ld_rlx2(mp + 16 * i); mc[i] = ld_rlx2(mp + D_ + 16 * i); }
    };
    if (wg < 2) {
#pragma unroll
      for (int k1 = 0; k1 < 9; k1++) lo[k1] = pin(sbase + O_Z1 + line_off(k1, kap, 4 * wg + t, cta & 3));
      float a[18], b[18];
#pragma unroll
      for (int i = 0; i < 9; i++) { a[2 * i] = bf_lo(xr[i]); a[2 * i + 1] = bf_hi(xr[i]); b[2 * i] = bf_lo(xr[9 + i]); b[2 * i + 1] = bf_hi(xr[9 + i]); }
      float oa, ra, ob, rb;
      ln_stats2(a, b, 1.0f, oa, ra, ob, rb);
      CK(1);
      const uint32_t sn = sbase + O_NRM + wp * 2336 + l * 4;
#pragma unroll
      for (int i = 0; i < 9; i++) {
        sts(sn + i * 128, pack_bf16(fmaf(a[2 * i], ra, oa), fmaf(a[2 * i + 1], ra, oa)));
        sts(sn + 1168 + i * 128, pack_bf16(fmaf(b[2 * i], rb, ob), fmaf(b[2 * i + 1], rb, ob)));
      }
      CK(2);
      bar_arrive(10, NTHR);
      load_mod();
#pragma unroll
      for (int kk = 0; kk < 4; kk++) af[kk] = ld_nc4(p.tab + TB_F + kk * 128 + (t128 ^ (wg << 5)));
      bar_sync(1, 256);
      if (tid == 0) TS(2);
    } else {
      bar_sync(10, NTHR);
      load_mod();
      CK(2);
      if (PFF && wp >= 12 - PFF && elect()) prefetch_l2(reinterpret_cast<const uint8_t*>(wp == 10 ? p.wr : p.wi) + cta * 9248, 9248);
      __syncwarp();
    }
    float rs[3][8];
#pragma unroll
    for (int i = 0; i < 3; i++) {
      uint32_t a0, a1, a2, a3;
      asm volatile("ldmatrix.sync.aligned.m8n8.x4.trans.shared.b16 {%0,%1,%2,%3}, [%4];" : "=r"(a0), "=r"(a1), "=r"(a2), "=r"(a3)
                   : "r"(snt + 32 * i) : "memory");
      mma16<false>(&rs[i][0], a0, a1, a2, a3, tb[0], tb[1]);
      mma16<false>(&rs[i][4], a0, a1, a2, a3, tb[2], tb[3]);
    }
    CK(3);
    {
      int it = 0;
#pragma unroll 1
      while (true) {
        uint32_t bad = 0;
#pragma unroll
        for (int i = 0; i < 3; i++) bad |= diff2(ms[i].x, ms[i].y, tag16) | diff2(mc[i].x, mc[i].y, tag16);
        if (!any(bad & 0xffffu) || ++it > SPIN_MAX) break;
        load_mod();
      }
      CK(4);
      if (tid == 0) TS(3);
#pragma unroll
      for (int i = 0; i < 3; i++) {
        const float c0 = bf_hi(mc[i].x), c1 = bf_hi(mc[i].y);
        const float s0 = __uint_as_float(ms[i].x & smask), s1 = __uint_as_float(ms[i].y & smask);
        stmatrix4(sb1[i], pack_bf16(fmaf(rs[i][0], c0, s0), rs[i][1] * c0), pack_bf16(fmaf(rs[i][2], c1, s1), rs[i][3] * c1),
                  pack_bf16(rs[i][4] * c0, rs[i][5] * c0), pack_bf16(rs[i][6] * c1, rs[i][7] * c1));
      }
    }
    fence_async_smem();
    CK(5);
    if (wg == 2) {
      bar_arrive(5, NTHR);
      if (R >= 0 && elect()) load_filter(wp - 8);
      __syncwarp();
    } else {
      bar_sync(5, NTHR);
      CK(6);
      float acc[36];
      const uint32_t db = (((sbase + O_B1 + wg * 9216) & 0x3FFFF) >> 4) | ((128 >> 4) << 16);
      wg_fence();
#pragma unroll
      for (int kk = 0; kk < 4; kk++) wgmma_rs_72(acc, af[kk].x, af[kk].y, af[kk].z, af[kk].w, db + kk * 16, 1024 >> 4, kk);
      wg_commit();
      wg_wait<0>();
      reg_fence(acc);
      CK(7);
      float2 za[9], zb[9];
#pragma unroll
      for (int i = 0; i < 9; i++) { za[i] = make_float2(acc[4 * i], acc[4 * i + 2]); zb[i] = make_float2(acc[4 * i + 1], acc[4 * i + 3]); }
      dft9(za); dft9(zb);
      if (kap == 0) {
#pragma unroll
        for (int k = 1; k < 5; k++) {
          float2 a = za[k], b = za[9 - k];
          za[k] = make_float2(a.x + b.x, a.y - b.y); za[9 - k] = make_float2(a.y + b.y, b.x - a.x);
          a = zb[k]; b = zb[9 - k];
          zb[k] = make_float2(a.x + b.x, a.y - b.y); zb[9 - k] = make_float2(a.y + b.y, b.x - a.x);
        }
        sts2(lo[0] + 288 * 8, set_tag(pack_bf16(za[0].y, 0.f), tag1), pack_bf16(zb[0].y, 0.f));
        za[0].y = 0.f; zb[0].y = 0.f;
      }
      __syncwarp();
#pragma unroll
      for (int k1 = 0; k1 < 9; k1++) sts2(lo[k1], set_tag(pack_bf16(za[k1].x, za[k1].y), tag1), pack_bf16(zb[k1].x, zb[k1].y));
      fence_async_smem();
      CK(8);
      bar_arrive(2 + wg, 160);
      {
        const uint32_t fx = (((cta >> 4) ^ cta) & 3) << 3, dl = O_IN - O_Z1, st = sbase + O_ST + 15360 + tid * 16;
        sts4(st, (lo[0] ^ fx) + dl, (lo[1] ^ fx) + dl, (lo[2] ^ fx) + dl, (lo[3] ^ fx) + dl);
        sts4(st + 4096, (lo[4] ^ fx) + dl, (lo[5] ^ fx) + dl, (lo[6] ^ fx) + dl, (lo[7] ^ fx) + dl);
        sts4(st + 8192, (lo[8] ^ fx) + dl, (lo[0] ^ fx) + dl + (kap ? 0 : 288 * 8),
             sbase + O_B3 + wg * 1024 + (l >> 4) * 2048 + (2 * (kap & 24) + (l & 15)) * 16, 0);
      }
    }
    {
      uint32_t sy[6];
#pragma unroll
      for (int i = 0; i < 6; i++) {
        const int rr = 16 * (wp & 3) + g + 8 * (i & 1);
        sy[i] = sbase + O_Y + (t * 584 + 64 * ((3 * wg + (i >> 1) + 63 - rr) % 9) + rr) * 4;
      }
      sts4(sbase + O_ST + tid * 16, movm(tb[0]), movm(tb[2]), movm(tb[1]), movm(tb[3]));
      sts4(sbase + O_ST + 6144 + tid * 16, sy[0], sy[1], sy[2], sy[3]);
      sts2(sbase + O_ST + 12288 + tid * 8, sy[4], sy[5]);
    }
  } else {
    __syncthreads();
  }

  if ((wp >> 1) == 4) {
    if (rows) {
      const int slot = 4 * (cta & 7) + ((cta >> 4) & 3) + 32 * (2 * (cta >> 6) + ((cta >> 3) & 1));
      const uint32_t c0 = upin(40 * slot), c1 = upin(60 * (wp - 8)), src = upin(sbase + O_Z1 + (wp - 8) * 9600);
      const CUtensorMap* mp = upin(&maps.z1);
      unsigned* hint = pin(&sc->cnt[C_Z1 + 32 * (wp - 8)]);
      bar_sync(wp - 6, 160);
      if (elect()) {
        tma_st2d(mp, src, c0, c1);
        HW();
        red_add(hint, 1);
        if (wp == 8) TS(4);
      }
    } else {
      int it = 0;
      while (any((ld_rlx(sc->moda + 36 * l) ^ tag16) & 0xffffu) && ++it < SPIN_MAX) {}
      if (elect()) { load_filter(wp - 8); load_filter(wp - 6); }
    }
    __syncwarp();
  }
  auto load_wm = [&](int u) {
    if (wp > 8 && elect()) {
      mbar_expect(full0 + 8 * B_WM, 6144);
      tma2d(sbase + O_NRM + (wp - 9) * 6144, &maps.wm, 16 * u, 192 * (wp - 9), full0 + 8 * B_WM);
    }
    __syncwarp();
  };
  if (R >= 0) {
    const int nl = (col0 + wp < DF_) + (wg < 2 && col0 + wp + 12 < DF_);
    uint4 cf[2][4], G[4];
#pragma unroll
    for (int i = 0; i < 4; i++) {
      cf[0][i] = __ldg(p.tab + TB_P2 + i * 32 + l);
      cf[1][i] = __ldg(p.tab + TB_P2 + (pi ? i : 4 + i) * 32 + l);
      G[i] = __ldg(p.tab + TB_P2 + (8 + i) * 32 + l);
    }
    const uint32_t* zin = sc->z1 + (size_t)R * 5120;
    if (wp == 10) {
      const uint32_t* zu = upin(zin);
      if (elect()) mbar_expect(full0 + 8 * B_Z1, 20480);
      wait_cnt(&sc->cnt[C_Z1 + 32 * (pi >> 2)], 128 * ep);
      if (elect()) {
        bulk_ld(sbase + O_P2, zu, 20480, full0 + 8 * B_Z1);
        TS(12);
      }
      __syncwarp();
    }
    mbar_wait(full0 + 8 * B_FLT, 0);
    CK(9);
    float wn[16], wc[16];
#pragma unroll 1
    for (int ln = nl - 1; ln >= 0; ln--) {
      const int col = col0 + wp + 12 * ln, k2 = (57 * col) & 63;
      const bool cj = k2 > 32 || (k2 == 32 && col != 288);
      const float nr = ((col & 31) == 0 && col != 0 && col != 288 ? 0.5f : 1.0f) / ((float)S_ * D_), ni = cj ? -nr : nr;
#pragma unroll
      for (int i = 0; i < 16; i++) wn[i] = wc[i];
#pragma unroll
      for (int cl = 0; cl < 2; cl++) {
        const int v = cl ^ (cj && pi), e = ((v ? xv : xu) & 15) + wp + 12 * ln, sh = e < 32 ? 6 : 5;
        const uint32_t base = sbase + O_RAW + v * 12288 + (e < 32 ? 2 * e : 8192 - 64 + 2 * e), msk = e < 32 ? 0x30 : 0x10;
        const int dm = v ? (cj || pi ? -1 : 0) : 0;
#pragma unroll
        for (int tt = 0; tt < 4; tt++) {
          const int kc = g + 64 * (tt >> 1) + 16 * t + 8 * (tt & 1);
          uint32_t a = base + ((((cj ? -kc : kc) + dm) & 127) << sh);
          a ^= (a >> 3) & msk;
          wc[4 * tt + 2 * cl] = lds_bf(a) * nr; wc[4 * tt + 2 * cl + 1] = lds_bf(a + 24576) * ni;
        }
      }
    }
    const float al = __uint_as_float(pin((pi ? 0x3f800000u : 0u) + (l >> 5)));
    const uint32_t tagv = pin(tag1 + (l >> 5));
    CK(10);
    uint32_t off = pin(l * 160 + ((wp ^ (g & 3)) << 3));
    uint32_t offo = pin(sbase + O_P2 + 20480 + off - 64 * l), po = 3072;
    unsigned* hz2 = pin(&sc->cnt[C_Z2]);
    const uint32_t do2 = pin(12288 - 32 * l);
    const CUtensorMap* mz2 = upin(&maps.z2[wp == 0]);
    const uint32_t sz2 = upin(sbase + O_P2 + 20480 + (wp ? 0 : 12288)), cz2 = upin(40 * R + (wp ? 0 : 24));
    mbar_wait(full0 + 8 * B_Z1, 0);
    CK(11);
    if (tid == 0) TS(8);
    if (wg == 2) load_wm(72 + cta);
    uint2 v[4], v2[4];
    const uint32_t o2 = nl > 1 ? 96 : 0;
#pragma unroll
    for (int i = 0; i < 4; i++) { v[i] = lds2(sbase + O_P2 + off + i * 5120); v2[i] = lds2(sbase + O_P2 + off + o2 + i * 5120); }
    auto bad2 = [&]() {
      return any(or3(or3(diff2(v[0].x, v[1].x, tagv), diff2(v[2].x, v[3].x, tagv), diff2(v2[0].x, v2[1].x, tagv)), diff2(v2[2].x, v2[3].x, tagv), 0) & 1);
    };
    if (__builtin_expect(bad2() && nl, 0)) {
      FAILCNT(0);
      int it = 0;
      do {
#pragma unroll
        for (int i = 0; i < 4; i++) {
          v[i] = ld_rlx2(reinterpret_cast<const uint8_t*>(zin) + off + i * 5120);
          v2[i] = ld_rlx2(reinterpret_cast<const uint8_t*>(zin) + off + o2 + i * 5120);
        }
      } while (bad2() && ++it < SPIN_MAX);
    }
#pragma unroll 1
    for (int ln = 0; ln < nl; ln++, offo += do2, po = 2048) {
      float d[4][4];
      uint32_t A[8];
#pragma unroll
      for (int h = 0; h < 2; h++) {
        mma16<false>(d[2 * h], cf[0][0].x, cf[0][0].y, cf[0][0].z, cf[0][0].w, v[h].x, v[2 + h].x);
        mma16<false>(d[2 * h + 1], cf[1][0].x, cf[1][0].y, cf[1][0].z, cf[1][0].w, v[h].y, v[2 + h].y);
      }
      if (ln) { fence_async_smem(); bar_arrive(15, NTHR); }
#pragma unroll
      for (int h = 0; h < 2; h++)
#pragma unroll
        for (int L = 0; L < 2; L++) {
          const uint4 tw = cf[L][2 + h];
          const float* z = d[2 * h + L];
          const float2 z0 = cmul(make_float2(z[0], z[2]), make_float2(__uint_as_float(tw.x), __uint_as_float(tw.y)));
          const float2 z1 = cmul(make_float2(z[1], z[3]), make_float2(__uint_as_float(tw.z), __uint_as_float(tw.w)));
          A[4 * h + L] = pack_bf16(z0.x, z0.y); A[4 * h + 2 + L] = pack_bf16(z1.x, z1.y);
        }
#pragma unroll
      for (int tt = 0; tt < 4; tt++) {
        mma16<false>(d[tt], A[0], A[1], A[2], A[3], G[tt].x, G[tt].y);
        mma16<true>(d[tt], A[4], A[5], A[6], A[7], G[tt].z, G[tt].w);
      }
#pragma unroll
      for (int tt = 0; tt < 4; tt++) {
        const float ar = d[tt][0], aj = d[tt][1], br = d[tt][2], bj = d[tt][3];
        const float2 y1 = cmul(make_float2(fmaf(-al, bj, ar), fmaf(al, br, aj)), make_float2(wc[4 * tt], wc[4 * tt + 1]));
        const float2 y2 = cmul(make_float2(fmaf(al, ar, bj), fmaf(al, aj, -br)), make_float2(wc[4 * tt + 2], wc[4 * tt + 3]));
        A[2 * tt] = pack_bf16(fmaf(al, y2.x, y1.x), fmaf(-al, y2.y, -y1.y));
        A[2 * tt + 1] = pack_bf16(fmaf(al, y1.y, -y2.y), fmaf(al, y1.x, -y2.x));
      }
#pragma unroll
      for (int i = 0; i < 16; i++) wc[i] = wn[i];
#pragma unroll
      for (int i = 0; i < 4; i++) v[i] = v2[i];
#pragma unroll
      for (int tt = 0; tt < 4; tt++) {
        mma16<false>(d[tt], A[0], A[1], A[2], A[3], G[tt].x, G[tt].y);
        mma16<true>(d[tt], A[4], A[5], A[6], A[7], G[tt].z, G[tt].w);
      }
#pragma unroll
      for (int h = 0; h < 2; h++)
#pragma unroll
        for (int L = 0; L < 2; L++) {
          const uint4 tw = cf[L][2 + h];
          const float2 z0 = cmul(make_float2(d[2 * h][2 * L], d[2 * h][2 * L + 1]), make_float2(__uint_as_float(tw.x), __uint_as_float(tw.y)));
          const float2 z1 = cmul(make_float2(d[2 * h + 1][2 * L], d[2 * h + 1][2 * L + 1]), make_float2(__uint_as_float(tw.z), __uint_as_float(tw.w)));
          A[4 * h + 2 * L] = movm(pack_bf16(z0.x, z1.x)); A[4 * h + 2 * L + 1] = movm(pack_bf16(z0.y, z1.y));
        }
#pragma unroll
      for (int h = 0; h < 2; h++) {
        mma16<false>(d[0], cf[0][1].x, cf[0][1].y, cf[0][1].z, cf[0][1].w, A[4 * h], A[4 * h + 1]);
        mma16<false>(d[1], cf[1][1].x, cf[1][1].y, cf[1][1].z, cf[1][1].w, A[4 * h + 2], A[4 * h + 3]);
#pragma unroll
        for (int e = 0; e < 2; e++)
          sts2(offo + (2 * h + e) * po, set_tag(pack_bf16(d[0][e], d[0][2 + e]), tagv), pack_bf16(d[1][e], d[1][2 + e]));
      }
      CK(12 + ln);
    }
    fence_async_smem();
    if (nl < 2 && wp != 8) bar_arrive(15, NTHR);
    if (wp & 7) { if (wg < 2) bar_arrive(6, 256); }
    else {
      if (wp) bar_sync(15, NTHR); else bar_sync(6, 256);
      if (elect()) {
        tma_st2d(mz2, sz2, cz2, 0);
        HW();
        if (wp == 0) { red_add(hz2, 1); TS(9); }
      }
      __syncwarp();
    }
  }
  if (wg == 2) {
#pragma unroll 1
    for (int u = 72 + cta, k = 0; u < 216; u += NCTA, k ^= 1) {
      if (R < 0) { fence_async_smem(); bar_sync(4, 128); load_wm(u); }
      mod_unit(sc, u, t128, sbase + O_NRM, full0 + 8 * B_WM, k, red + 256 - 256 * k, tag16);
    }
    fence_async_smem();
    CK(13);
  }

  const int grp = cta / 11, m1 = cta - 11 * grp;
  const bool helper = (m1 & 3) == 3;
  const int f1 = 384 * grp + (helper ? 192 : 128) * (m1 >> 2);
  const int d1 = 160 * (m1 & 3), flip = m1 >= 7;
  const int a1bytes = helper ? 24576 : 16384;
  auto load_a1 = [&](int st, int kb) {
    mbar_expect(full0 + 8 * st, a1bytes);
    tma4d_ef(sbase + st * STAGE, helper ? &maps.w1b : &maps.w1a, 4 * (kb >> 3), 16 * (kb & 7), f1 >> 6, full0 + 8 * st);
  };

  if (rows) {
#pragma unroll
    for (int kk = 0; kk < 4; kk++) af[kk] = __ldg(p.tab + TB_E + kk * 128 + t128);
    const uint4 c0 = lds4(sbase + O_ST + tid * 16), c1 = lds4(sbase + O_ST + 6144 + tid * 16);
    const uint2 c2 = lds2(sbase + O_ST + 12288 + tid * 8);
    const uint32_t tb[4] = {c0.x, c0.y, c0.z, c0.w}, sy[6] = {c1.x, c1.y, c1.z, c1.w, c2.x, c2.y};
    const uint32_t l8 = pin(8 * l), syl = pin(sbase + O_Y + wp * 2336 + 8 * l);
    const uint32_t sh3 = pin(sbase + O_B3 + (wp >> 1) * 4608 + (l >> 4) * 256 + (wp & 1) * 128 + ((((l >> 2) ^ (2 * cta + (wp & 1))) & 3) << 4) + (l & 3) * 4);
    const bool htag = (((sh3 >> 2) ^ (2 * cta + (wp & 1))) & 7) == 0;
    const uint32_t ham = pin(htag ? ~1u : ~0u), hom = pin(htag ? tag1 : 0u);
    const int slot = 4 * (cta >> 4) + ((cta >> 1) & 3) + 32 * (2 * ((cta >> 3) & 1) + (cta & 1));
    const uint32_t* zin = sc->z2 + (size_t)slot * 4800;
    if (wg == 2) {
      {
        uint4 v[4];
        const int i3 = min(t128 + 384, 431);
        int it = 0;
        while (true) {
          uint32_t bad = 0;
#pragma unroll
          for (int k = 0; k < 4; k++) v[k] = ld_rlx4(sc->mod + 4 * (k < 3 ? t128 + 128 * k : i3));
#pragma unroll
          for (int k = 0; k < 4; k++) {
            v[k].x ^= tag16; v[k].y ^= tag16; v[k].z ^= tag16; v[k].w ^= tag16;
            bad |= v[k].x | v[k].y | v[k].z | v[k].w;
          }
          if (!any(bad & 0xffffu) || ++it > SPIN_MAX) break;
        }
#pragma unroll
        for (int k = 0; k < 4; k++) sts4(sbase + O_MOD + 16 * (k < 3 ? t128 + 128 * k : i3), v[k].x, v[k].y, v[k].z, v[k].w);
      }
      CK(14);
      bar_sync(10, NTHR);
      mbar_wait(full0 + 8 * B_Z2, 0);
      if (elect()) {
        load_a1(wp - 8, wp - 8);
        if (wp > 8 && wp - 8 < NG1) prefetch_l2(reinterpret_cast<const uint8_t*>(p.w1) + (size_t)(128 * (4 * ((wp - 8) >> 1) + (cta >> 5)) + 64 * (wp & 1) + 2 * (cta & 31)) * (2 * F_), 4 * F_);
      }
      __syncwarp();
    } else {
      const uint4 e0 = lds4(sbase + O_ST + 15360 + tid * 16), e1 = lds4(sbase + O_ST + 19456 + tid * 16), e2 = lds4(sbase + O_ST + 23552 + tid * 16);
      const uint32_t lo[9] = {e0.x, e0.y, e0.z, e0.w, e1.x, e1.y, e1.z, e1.w, e2.x}, lx = e2.y, sb3 = e2.z;
      bar_arrive(10, NTHR);
      CK(14);
      if (wp == 1) {
        const uint32_t* zu = upin(zin);
        if (elect()) mbar_expect(full0 + 8 * B_Z2, 19200);
        wait_cnt(&sc->cnt[C_Z2], 120 * ep);
        if (elect()) {
          bulk_ld(sbase + O_IN, zu, 19200, full0 + 8 * B_Z2);
          TS(14);
        }
        __syncwarp();
      }
      mbar_wait(full0 + 8 * B_Z2, 0);
      CK(15);
      if (tid == 0) TS(11);
      uint2 v[10];
#pragma unroll
      for (int k1 = 0; k1 < 10; k1++) v[k1] = lds2(k1 < 9 ? lo[k1] : lx);
      auto bad3 = [&]() {
        return any(or3(or3(diff2(v[0].x, v[1].x, tag1), diff2(v[2].x, v[3].x, tag1), diff2(v[4].x, v[5].x, tag1)), diff2(v[6].x, v[7].x, tag1), diff2(v[8].x, v[9].x, tag1)) & 1);
      };
      if (__builtin_expect(bad3(), 0)) {
        FAILCNT(1);
        int it = 0;
        do {
#pragma unroll
          for (int k1 = 0; k1 < 10; k1++) v[k1] = ld_rlx2(reinterpret_cast<const uint8_t*>(zin) + ((k1 < 9 ? lo[k1] : lx) - (sbase + O_IN)));
        } while (bad3() && ++it < SPIN_MAX);
      }
      float2 za[9], zb[9];
#pragma unroll
      for (int i = 0; i < 9; i++) { za[i] = make_float2(bf_lo(v[i].x), bf_hi(v[i].x)); zb[i] = make_float2(bf_lo(v[i].y), bf_hi(v[i].y)); }
      if (kap == 0) {
#pragma unroll
        for (int k = 1; k < 5; k++) {
          float2 a = za[k], b = za[9 - k];
          za[k] = make_float2(a.x - b.y, a.y + b.x); za[9 - k] = make_float2(a.x + b.y, b.x - a.y);
          a = zb[k]; b = zb[9 - k];
          zb[k] = make_float2(a.x - b.y, a.y + b.x); zb[9 - k] = make_float2(a.x + b.y, b.x - a.y);
        }
        za[0].y = bf_lo(v[9].x); zb[0].y = bf_lo(v[9].y);
      }
      __syncwarp();
      dft9(za); dft9(zb);
#pragma unroll
      for (int n = 0; n < 8; n += 2) {
        const int i0 = (9 - n) % 9, i1 = 8 - n;
        stmatrix4(sb3 + n * 2048, pack_bf16(za[i0].x, zb[i0].x), pack_bf16(za[i0].y, zb[i0].y), pack_bf16(za[i1].x, zb[i1].x), pack_bf16(za[i1].y, zb[i1].y));
      }
      stmatrix2(sb3 + 8 * 2048, pack_bf16(za[1].x, zb[1].x), pack_bf16(za[1].y, zb[1].y));
      fence_async_smem();
    }
    CK(16);
    __syncthreads();
    CK(17);
    float acc[24];
    const uint32_t db = (((sbase + O_B3 + wg * 6144) & 0x3FFFF) >> 4) | ((128 >> 4) << 16);
    wg_fence();
#pragma unroll
    for (int kk = 0; kk < 4; kk++) wgmma_rs_48(acc, af[kk].x, af[kk].y, af[kk].z, af[kk].w, db + kk * 16, 1024 >> 4, kk);
    wg_commit();
    uint32_t ga[9];
    uint2 sh[9], sw[9];
    if (wg < 2) {
#pragma unroll
      for (int i = 0; i < 9; i++) {
        const uint2 v = lds2(l8 + sbase + O_MOD + 256 * i);
        ga[i] = __byte_perm(v.x, v.y, 0x7632);
        sh[i] = lds2(l8 + sbase + O_MOD + 4 * D_ + 256 * i);
        sw[i] = lds2(l8 + sbase + O_MOD + 8 * D_ + 256 * i);
      }
    }
    wg_wait<0>();
    reg_fence(acc);
    CK(18);
#pragma unroll
    for (int i = 0; i < 3; i++) {
      const float* a = &acc[8 * i];
      const uint32_t a0 = pack_bf16(a[0], a[1]), a1 = pack_bf16(a[2], a[3]), a2 = pack_bf16(a[4], a[5]), a3 = pack_bf16(a[6], a[7]);
#pragma unroll
      for (int jh = 0; jh < 2; jh++) {
        float y[4];
        mma16<false>(y, a0, a1, a2, a3, tb[2 * jh], tb[2 * jh + 1]);
        sts(sy[2 * i] + jh * (4 * 584 * 4), pack_bf16(y[0], y[1]));
        sts(sy[2 * i + 1] + jh * (4 * 584 * 4), pack_bf16(y[2], y[3]));
      }
    }
    CK(19);
    if (wg == 2) bar_arrive(7, NTHR);
    else {
      bar_sync(7, NTHR);
      CK(20);
      float a[18], b[18];
#pragma unroll
      for (int i = 0; i < 9; i++) {
        const uint2 y = lds2(syl + 256 * i);
        xr[i] = hfma2(ga[i], __byte_perm(y.x, y.y, 0x5410), xr[i]);
        xr[9 + i] = hfma2(ga[i], __byte_perm(y.x, y.y, 0x7632), xr[9 + i]);
        a[2 * i] = bf_lo(xr[i]); a[2 * i + 1] = bf_hi(xr[i]); b[2 * i] = bf_lo(xr[9 + i]); b[2 * i + 1] = bf_hi(xr[9 + i]);
      }
      float oa, ra, ob, rb;
      ln_stats2(a, b, 1.0f, oa, ra, ob, rb);
      CK(21);
#pragma unroll
      for (int i = 0; i < 9; i++) {
        const float c0 = __uint_as_float(sw[i].x), c1 = __uint_as_float(sw[i].y), s0 = __uint_as_float(sh[i].x), s1 = __uint_as_float(sh[i].y);
        a[2 * i] = fmaf(fmaf(a[2 * i], ra, oa), c0, s0); a[2 * i + 1] = fmaf(fmaf(a[2 * i + 1], ra, oa), c1, s1);
        b[2 * i] = fmaf(fmaf(b[2 * i], rb, ob), c0, s0); b[2 * i + 1] = fmaf(fmaf(b[2 * i + 1], rb, ob), c1, s1);
      }
      ln_stats2(a, b, 0.5f, oa, ra, ob, rb);
      CK(22);
#pragma unroll
      for (int i = 0; i < 9; i++) {
        sts(sh3 + i * 512, and_or(pack_bf16(fmaf(a[2 * i], ra, oa), fmaf(a[2 * i + 1], ra, oa)), ham, hom));
        sts(sh3 + i * 512 + 64, and_or(pack_bf16(fmaf(b[2 * i], rb, ob), fmaf(b[2 * i + 1], rb, ob)), ham, hom));
      }
      fence_async_smem();
      if (wp == 0) CKX(0);
      if (wp < 2 * H3G) bar_arrive(8, 32 + 64 * H3G); else bar_arrive(9, 288 - 64 * H3G);
      CK(23);
    }
  } else __syncthreads();

  const bool g2 = cta < 130 && (cta >> 1) != 56;
  const int z2 = cta < 112 ? cta : cta - 2, r = z2 >> 6;
  const int s2 = 128 * ((z2 >> 2) & 15), d2 = 144 * (z2 & 3);
  constexpr int XST = (33 + 36 - JSK - 1) % NST;
  constexpr int ST0 = (32 - JSK - 1) % NST, ST1 = 31 % NST;

  if (wg == 2) {
    asm volatile("setmaxnreg.dec.sync.aligned.u32 40;");
    auto load_b = [&](bool second, int i, int st) {
      const uint32_t lb = full0 + 8 * (B_LAND + st), bytes = second ? 18432 : STAGE - a1bytes;
      mbar_expect(lb, bytes);
      bulk_ld(sbase + st * STAGE + (second ? 16384 : a1bytes),
              second ? sc->u + ((size_t)(36 * r + kb2_order(i)) * D_ + d2) * 128 : sc->h3 + ((size_t)(i * 18 + (d1 >> 5)) << 12), bytes, lb);
    };
    if (wp == 8) {
      int st = rows ? 4 : 0, ph = 1;
#pragma unroll 1
      for (int kb = st; kb < 32; kb++) {
        if (rows && (kb >> 1) == 2) mbar_wait(full0 + 8 * (B_S4 - 4 + kb), 0);
        mbar_wait(empty0 + 8 * st, ph);
        if (elect()) {
          load_a1(st, kb);
          if (kb >= PF2K && kb < PF2K + PF2 && g2)
            prefetch_l2(reinterpret_cast<const uint8_t*>(p.w2) + (size_t)(36 * r + kb2_order(kb - PF2K)) * 262144 + (z2 & 63) * 4096, 4096);
        }
        __syncwarp();
        ring_next<false>(st, ph);
      }
      if (g2) {
        st++;
#pragma unroll 1
        for (int i = 0; i < 36; i++) {
          if (i == HOLDA) mbar_wait(full0 + 8 * B_GO, 0);
          mbar_wait(empty0 + 8 * st, ph);
          if (elect()) {
            mbar_expect(full0 + 8 * st, 16384);
            tma3d_ef(sbase + st * STAGE, &maps.w2, 64 * (36 * r + kb2_order(i)), s2 >> 6, full0 + 8 * st);
          }
          __syncwarp();
          ring_next<true>(st, ph);
        }
      }
    } else if (wp >= 10) {
      const int sw = wp - 10;
      if (rows) {
        const CUtensorMap* mp = upin(&maps.h3[sw]);
        const uint32_t src = upin(sbase + O_B3 + sw * (H3G * 4608)), c0 = upin(64 * (cta & 15)), c1 = upin(18 * (cta >> 4)), c2 = upin(H3G * sw);
        unsigned* flag = pin(&sc->cnt[C_H3 + (cta >> 4) + 8 * sw]);
        bar_sync(8 + sw, sw ? 288 - 64 * H3G : 32 + 64 * H3G);
        if (!sw) CKX(1);
        if (sw) { mbar_wait(full0 + 8 * H3W, 0); CKX(7); }
        if (elect()) {
          tma_st3d(mp, src, c0, c1, c2);
          if (!sw) CKX(2);
          mbar_arrive(full0 + 8 * B_S4);
          bulk_commit_wait();
          if (!sw) CKX(3);
          red_add(flag, 1);
          mbar_arrive(full0 + 8 * B_S5);
          if (!sw) CKX(4);
          TS(sw ? 24 : 13);
        }
        __syncwarp();
      }
      if (sw) {
        if (rows) {
          mbar_wait(full0 + 8 * B_S5, 0);
          if (elect()) { asm volatile("fence.acq_rel.gpu;" ::: "memory"); red_add(&sc->cnt[C_X + 64], 1); }
          __syncwarp();
        }
        wait_cnt(&sc->cnt[C_X + 64], 128 * ep);
        if (elect()) mbar_arrive(full0 + 8 * B_X);
        __syncwarp();
      }
      if (sw && g2) {
#pragma unroll 1
        for (int i = 0; i < 36; i++) { sc->part[z2 * 1152 + 32 * i + l] = make_uint4(tag1 ^ 1, 0, 0, 0); __nanosleep(100); }
        __syncwarp();
      }
      uint32_t lph = 0;
      auto check_tiles = [&](bool second, int n, int st, uint32_t o1, uint32_t d2nd) {
        const uint32_t b1 = pin(sbase + o1), b2 = pin(sbase + o1 + d2nd);
        int i = 0, it = 0;
#pragma unroll 1
        do {
          const uint32_t so = st * STAGE;
          mbar_wait(full0 + 8 * (B_LAND + st), (lph >> st) & 1);
          lph ^= 1u << st;
          uint32_t v[20];
#pragma unroll
          for (int k = 0; k < 20; k++) if (!second || k < 10 || k >= 12) v[k] = lds(k < 12 ? b1 + so + k * 1024 : b2 + so + (k - 12) * 1024); else v[k] = tag1;
#pragma unroll
          for (int k = 0; k < 10; k++) v[k] = diff2(v[2 * k], v[2 * k + 1], tag1);
          const uint32_t bad = or3(or3(or3(v[0], v[1], v[2]), or3(v[3], v[4], v[5]), v[6]), v[7], or3(v[8], v[9], 0));
          if (__builtin_expect(any(bad & 1) && ++it < SPIN_MAX, 0)) {
            FAILCNT(2 + second);
            fence_async_smem();
            __syncwarp();
            if (elect()) load_b(second, i, st);
            __syncwarp();
            continue;
          }
          if (elect()) mbar_arrive(full0 + 8 * st);
          if (second && i < 6) CKX(12 + 3 * i);
          st = ((second ? 0x054132u : 0x054321u) >> (4 * st)) & 7;
          i++;
        } while (i < n);
      };
      if (!sw) check_tiles(false, NV1, 0, a1bytes + l * 32 + (l >> 2) * 4, helper ? 4096 : 12288);
      const uint32_t stg = sbase + (sw ? ST1 : ST0) * STAGE;
      const int kbA = (f1 >> 6) + (helper ? 2 : 1) * (sw ^ flip), kbB = helper ? (f1 >> 6) + 1 : kbA;
      const int dB = helper ? d1 : d1 + 96;
      uint8_t* const uA = upin(sc->u + ((size_t)kbA * D_ + d1) * 128);
      uint8_t* const uB = upin(sc->u + ((size_t)kbB * D_ + dB) * 128);
      unsigned* const fA = pin(&sc->cnt[C_U + kbA]);
      unsigned* const fB = pin(&sc->cnt[C_U + kbB]);
      bar_sync(11 + sw, 160);
      if (sw && g2) mbar_wait(full0 + 8 * B_GO, 0);
      if (elect()) { bulk_st(uA, stg, 96 * 128); TS(sw ? 31 : 30); }
      __syncwarp();
      if (!helper || sw) bar_sync(13 + sw, 160);
      if (elect()) {
        if (!helper || sw) bulk_st(uB, stg + 96 * 128, helper ? 96 * 128 : 64 * 128);
        bulk_commit_wait();
        red_add(fA, 1);
        if (WAITALL) red_add(&sc->cnt[C_X + 32], 1);
        if (helper && sw) red_add(fB, 1);
        mbar_arrive(empty0 + 8 * (sw ? ST1 : ST0));
        TS(sw ? 23 : 17);
        mbar_arrive(full0 + 8 * B_S5);
      }
      __syncwarp();
      if (sw) {
        mbar_wait(full0 + 8 * B_S5, rows);
        if (elect()) { asm volatile("fence.acq_rel.gpu;" ::: "memory"); red_add(&sc->cnt[C_X], 1); }
        __syncwarp();
      }
      if (g2) {
        if (!sw) check_tiles(true, NV2, 3, 16384 + l * 32 + (4 * (g & 1) + (g >> 1)) * 4, 10240);
        else {
          wait_cnt(&sc->cnt[C_X], NCTA * ep);
          if (elect()) mbar_arrive(full0 + 8 * B_X);
        }
      }
      __syncwarp();
    } else {
      uint64_t ready = 0;
      int st = 0, ph = 1;
#pragma unroll 1
      for (int kb = 0; kb < 32; kb++) {
        const uint8_t* src = upin(sc->h3 + ((size_t)(kb * 18 + (d1 >> 5)) << 12));
        const uint32_t dst = upin(sbase + st * STAGE + a1bytes), lb = full0 + 8 * ((kb < NV1 ? B_LAND : 0) + st);
        if (kb == NV1) { mbar_wait(full0 + 8 * B_X, 0); fence_async_glb(); ready = ~0ull; }
        if (rows && (kb >> 1) == 2) mbar_wait(full0 + 8 * (B_S4 - 4 + kb), 0);
        mbar_wait(empty0 + 8 * st, ph);
        if (elect()) mbar_expect(lb, STAGE - a1bytes);
        wait_flags(sc->cnt + C_H3, 32, (kb & 7) + (kb < 8 * H3G ? 0 : 8), 16 * ep, ready);
        if (kb == 0) CKX(5);
        if (elect()) bulk_ld(dst, src, STAGE - a1bytes, lb);
        if (kb == 0) CKX(6);
        if (kb == 5) CKX(8);
        if (kb == 8 * H3G) CKX(9);
        ring_next<false>(st, ph);
      }
      if (g2) {
        ready = 0;
        st++;
#pragma unroll 1
        for (int i = 0; i < 36; i++) {
          const int kb = kb2_order(i);
          const uint8_t* src = upin(sc->u + ((size_t)(36 * r + kb) * D_ + d2) * 128);
          const uint32_t dst = upin(sbase + st * STAGE + 16384), lb = full0 + 8 * ((i < NV2 ? B_LAND : 0) + st);
          if (i == NV2) { mbar_wait(full0 + 8 * B_X, 1); fence_async_glb(); ready = ~0ull; }
          mbar_wait(empty0 + 8 * st, ph);
          if (elect()) mbar_expect(lb, 18432);
          wait_flags(sc->cnt + C_U + 36 * r, 36, kb, 4 * ep, ready);
          if (elect()) {
            bulk_ld(dst, src, 18432, lb);
            if (i == GOAT) mbar_arrive(full0 + 8 * B_GO);
          }
          if (i < 6) CKX(10 + 3 * i);
          ring_next<true>(st, ph);
        }
        mbar_wait(empty0 + 8 * st, ph);
        if (elect()) {
          mbar_arrive(full0 + 8 * XST);
          mbar_expect(full0 + 8 * XST, 18432);
#pragma unroll 1
          for (int i = 0; i < 3; i++) tma2d(sbase + XST * STAGE + 18432 + i * 6144, &maps.x1, d2 + 48 * i, s2 + 64 * (r ^ 1), full0 + 8 * XST);
        }
        __syncwarp();
      }
    }
  } else {
    asm volatile("setmaxnreg.inc.sync.aligned.u32 232;");
    const int wgu = wg;
    constexpr uint32_t sb4 = sbase >> 4;
    const int w = wp & 3;
    Ring rg = {0, 0};
    uint32_t* const x1p = sc->x1 + (size_t)(cta + 256 * wp) * 288 + l;
    const uint32_t ad = pin(sbase + (wg ? ST1 : ST0) * STAGE + (8 * (l >> 4) + (l & 7)) * 128 + (((2 * w + ((l >> 3) & 1)) ^ (l & 7)) << 4));
    const uint32_t uam = pin(g == 2 * t ? 0xfffefffeu : ~0u), uom = pin(g == 2 * t ? tag1 * 0x10001u : 0u);
    float acc[96];
    constexpr uint32_t LA = (8192 >> 4) << 16, LB = (4096 >> 4) << 16;
    {
      const int fa = f1 + (helper ? 128 : 64) * (wg ^ flip) + 16 * w + g, fb = helper ? f1 + 64 + 16 * w + g : fa;
      const float a0 = 0.5f * __bfloat162float(p.b1[fa]), a1 = 0.5f * __bfloat162float(p.b1[fa + 8]);
      const float b0 = 0.5f * __bfloat162float(p.b1[fb]), b1 = 0.5f * __bfloat162float(p.b1[fb + 8]);
#pragma unroll
      for (int i = 0; i < 96; i++) acc[i] = i < 48 ? ((i & 2) ? a1 : a0) : ((i & 2) ? b1 : b0);
      reg_fence(acc);
    }
    if (!helper) gemm_main<0>(acc, sb4 + (wgu ^ flip) * 512 + LA, 0, sb4 + 1024 + LB, wgu, rg, x1p, xr);
    else {
      float ac2[96];
#pragma unroll
      for (int i = 0; i < 96; i++) asm volatile("mov.b32 %0, %1;" : "=f"(ac2[i]) : "f"(acc[i]));
      gemm_main<1>(ac2, sb4 + (wgu ^ flip) * 1024 + LA, sb4 + 512 + LA, sb4 + 1536 + LB, wgu, rg, x1p, xr);
#pragma unroll
      for (int i = 0; i < 96; i++) asm volatile("mov.b32 %0, %1;" : "=f"(acc[i]) : "f"(ac2[i]));
    }
    if (t128 == 0) TS(wg ? 16 : 6);
    {
      float z[2][16];
      auto put = [&](int j, const float* tt) {
        const float* a = &acc[16 * j];
#pragma unroll
        for (int h = 0; h < 16; h += 8)
          stmatrix4t(ad + (2 * j + (h >> 3)) * 2048, and_or(pack_bf16(fmaf(a[h], tt[h], a[h]), fmaf(a[h + 1], tt[h + 1], a[h + 1])), uam, uom),
                     pack_bf16(fmaf(a[h + 2], tt[h + 2], a[h + 2]), fmaf(a[h + 3], tt[h + 3], a[h + 3])),
                     and_or(pack_bf16(fmaf(a[h + 4], tt[h + 4], a[h + 4]), fmaf(a[h + 5], tt[h + 5], a[h + 5])), uam, uom),
                     pack_bf16(fmaf(a[h + 6], tt[h + 6], a[h + 6]), fmaf(a[h + 7], tt[h + 7], a[h + 7])));
      };
#pragma unroll
      for (int j = -1; j <= 5; j++) {
        if (j >= 1) put(j - 1, z[(j - 1) & 1]);
        if (j == 5 && helper) {
#pragma unroll
          for (int e = 0; e < 16; e++) { z[1][e] = gelu_arg(acc[80 + e]); asm("tanh.approx.f32 %0, %0;" : "+f"(z[1][e])); }
          put(5, z[1]);
        }
        if (j >= 0 && j < 5) {
#pragma unroll
          for (int e = 0; e < 16; e++) asm("tanh.approx.f32 %0, %0;" : "+f"(z[j & 1][e]));
        }
        if (j < 4) {
#pragma unroll
          for (int e = 0; e < 16; e++) z[(j + 1) & 1][e] = gelu_arg(acc[16 * (j + 1) + e]);
        }
        if (j == 3 || j == 5) { fence_async_smem(); asm volatile("bar.arrive %0, 160;" ::"r"((j == 3 ? 11 : 13) + wgu) : "memory"); }
        if (j == 3 && helper && !wgu) break;
        if (j < 5) {
          if (j >= 0) reg_fence(z[j & 1]);
          if (j < 4) reg_fence(z[(j + 1) & 1]);
          if (__builtin_expect(wp == 0x7ffffff0 + j, 0)) __trap();
          reg_fence(acc);
        }
      }
      if (t128 == 0) TS(wg ? 29 : 28);
    }
    if (g2) {
      const int mb = wgu ^ r;
      uint32_t gb[18];
      {
        float a0 = 0.f, a1 = 0.f;
        if (wgu) {
          a0 = __bfloat162float(p.b2[s2 + 64 * mb + 16 * w + g]); a1 = __bfloat162float(p.b2[s2 + 64 * mb + 16 * w + 8 + g]);
          int it = 0;
          uint32_t bad;
          do {
            bad = 0;
#pragma unroll
            for (int i = 0; i < 18; i++) {
              const uint2 v = ld_rlx2(sc->mod + 3 * D_ + d2 + 8 * i + 2 * t);
              bad |= (v.x ^ tag16) | (v.y ^ tag16);
              gb[i] = __byte_perm(v.x, v.y, 0x7632);
            }
          } while (any(bad & 0xffffu) && ++it < SPIN_MAX);
        }
#pragma unroll
        for (int i = 0; i < 72; i++) acc[i] = (i & 2) ? a1 : a0;
      }
      rg.st++;
      gemm_main<3>(acc, sb4 + mb * 512 + LA, 0, sb4 + 1024 + (1 << 16), wgu, rg, x1p, xr);
      if (t128 == 0) TS(wg ? 20 : 19);
      const uint32_t sx = sbase + XST * STAGE;
      if (wgu == 0) {
        uint4* dst = sc->part + z2 * 1152 + t128;
#pragma unroll
        for (int j = 0; j < 9; j++) {
          const float* a = &acc[8 * j];
          dst[j * 128] = make_uint4(set_tag(pack_bf16(a[0], a[1]), tag1), pack_bf16(a[2], a[3]), pack_bf16(a[4], a[5]), pack_bf16(a[6], a[7]));
        }
        if (tid == 0) TS(21);
        const uint4* src = sc->part + (z2 ^ 64) * 1152 + t128;
        uint4 v[9];
        uint32_t bad;
        int it = 0;
        do {
#pragma unroll
          for (int j = 0; j < 9; j++) v[j] = ld_rlx4(src + j * 128);
          bad = or3(or3(diff2(v[0].x, v[1].x, tag1), diff2(v[2].x, v[3].x, tag1), diff2(v[4].x, v[5].x, tag1)), diff2(v[6].x, v[7].x, tag1), v[8].x ^ tag1);
        } while (any(bad & 1) && ++it < SPIN_MAX);
#pragma unroll
        for (int j = 0; j < 9; j++) sts4(sx + t128 * 16 + j * 2048, v[j].x, v[j].y, v[j].z, v[j].w);
        bar_arrive(2 + w, 64);
        if (w == 0) {
#pragma unroll 1
          for (int i = 0; i < 3; i++) {
            bar_sync(11 + i, 160);
            if (elect()) tma_st2d(&maps.out, sx + 18432 + i * 6144, d2 + 48 * i, s2 + 64 * (r ^ 1));
            __syncwarp();
          }
          if (elect()) { bulk_commit_wait_read(); TS(22); }
          __syncwarp();
        }
      } else {
        mbar_wait(full0 + 8 * XST, rg.ph);
        bar_sync(2 + w, 64);
        if (t128 == 0) TS(5);
        if (tid == 128 && cta == 0) sc->cnt[C_EP] = ep;
        const uint32_t xa = sx + 18432 + (16 * w + (l & 15)) * 96 + (l >> 4) * 16;
#pragma unroll
        for (int c = 0; c < 3; c++) {
          uint32_t pv[3][4], xv[3][4];
#pragma unroll
          for (int j = 0; j < 3; j++) {
            asm volatile("ld.shared.v4.b32 {%0,%1,%2,%3}, [%4];" : "=r"(pv[j][0]), "=r"(pv[j][1]), "=r"(pv[j][2]), "=r"(pv[j][3]) : "r"(sx + t128 * 16 + (3 * c + j) * 2048) : "memory");
            asm volatile("ldmatrix.sync.aligned.m8n8.x4.shared.b16 {%0,%1,%2,%3}, [%4];" : "=r"(xv[j][0]), "=r"(xv[j][1]), "=r"(xv[j][2]), "=r"(xv[j][3]) : "r"(xa + c * 6144 + j * 32) : "memory");
          }
#pragma unroll
          for (int j = 0; j < 3; j++) {
            const float* a = &acc[8 * (3 * c + j)];
            uint32_t o[4];
#pragma unroll
            for (int e = 0; e < 4; e++)
              o[e] = hadd2(xv[j][e], hmul2(gb[2 * (3 * c + j) + (e >> 1)], pack_bf16(a[2 * e] + bf_lo(pv[j][e]), a[2 * e + 1] + bf_hi(pv[j][e]))));
            stmatrix4(xa + c * 6144 + j * 32, o[0], o[1], o[2], o[3]);
          }
          fence_async_smem();
          asm volatile("bar.arrive %0, 160;" ::"r"(11 + c) : "memory");
        }
        if (t128 == 0) TS(7);
        __syncwarp();
      }
    }
  }
}

typedef CUresult (*EncodeFn)(CUtensorMap*, CUtensorMapDataType, cuuint32_t, void*, const cuuint64_t*, const cuuint64_t*, const cuuint32_t*,
                             const cuuint32_t*, CUtensorMapInterleave, CUtensorMapSwizzle, CUtensorMapL2promotion, CUtensorMapFloatOOBfill);

struct Dim { cuuint64_t n, stride; cuuint32_t box; };
template <int RANK>
void make_map(EncodeFn enc, CUtensorMap* m, bool words, int swz, const void* ptr, const Dim (&d)[RANK]) {
  cuuint64_t gd[RANK], gs[RANK];
  cuuint32_t bx[RANK], es[RANK];
  for (int i = 0; i < RANK; i++) { gd[i] = d[i].n; gs[i] = d[i].stride; bx[i] = d[i].box; es[i] = 1; }
  enc(m, words ? CU_TENSOR_MAP_DATA_TYPE_UINT32 : CU_TENSOR_MAP_DATA_TYPE_BFLOAT16, RANK, const_cast<void*>(ptr), gd, gs + 1, bx, es,
      CU_TENSOR_MAP_INTERLEAVE_NONE, static_cast<CUtensorMapSwizzle>(swz),
      swz == 3 ? CU_TENSOR_MAP_L2_PROMOTION_L2_256B : CU_TENSOR_MAP_L2_PROMOTION_NONE, CU_TENSOR_MAP_FLOAT_OOB_FILL_NONE);
}

}

extern "C" void kernel_launch(void* const* d_in, const int* in_sizes, int n_in, void* d_out, int out_size) {
  (void)in_sizes; (void)n_in; (void)out_size;
  static EncodeFn enc = nullptr;
  static void *sptr = nullptr, *tptr = nullptr;
  if (!enc) {
    void* f = nullptr; cudaDriverEntryPointQueryResult qr;
    cudaGetDriverEntryPoint("cuTensorMapEncodeTiled", &f, cudaEnableDefault, &qr);
    enc = reinterpret_cast<EncodeFn>(f);
    cudaFuncSetAttribute(fused_kernel, cudaFuncAttributeMaxDynamicSharedMemorySize, SMEM_BYTES);
    cudaGetSymbolAddress(&sptr, g_s);
    cudaGetSymbolAddress(&tptr, T_TAB);
  }
  Params p;
  p.x = (const __nv_bfloat16*)d_in[0]; p.wr = (const __nv_bfloat16*)d_in[1]; p.wi = (const __nv_bfloat16*)d_in[2];
  p.b1 = (const __nv_bfloat16*)d_in[5]; p.b2 = (const __nv_bfloat16*)d_in[7];
  p.c = (const __nv_bfloat16*)d_in[8]; p.wmod = (const __nv_bfloat16*)d_in[9];
  p.w1 = (const __nv_bfloat16*)d_in[4]; p.w2 = (const __nv_bfloat16*)d_in[6];
  p.s = static_cast<Scratch*>(sptr); p.tab = static_cast<const uint4*>(tptr);
  Maps maps;
  make_map<4>(enc, &maps.w1a, false, 3, p.w1, {{64, 0, 64}, {16, 128 * 2 * F_, 4}, {128, 2 * F_, 16}, {72, 128, 2}});
  make_map<4>(enc, &maps.w1b, false, 3, p.w1, {{64, 0, 64}, {16, 128 * 2 * F_, 4}, {128, 2 * F_, 16}, {72, 128, 3}});
  make_map<3>(enc, &maps.w2, false, 3, p.w2, {{64, 0, 64}, {F_, 2 * S_, 64}, {32, 128, 2}});
  make_map<2>(enc, &maps.x1, false, 0, p.s->x1, {{D_, 0, 48}, {S_, 2 * D_, 64}});
  make_map<2>(enc, &maps.out, false, 0, d_out, {{D_, 0, 48}, {S_, 2 * D_, 64}});
  make_map<2>(enc, &maps.z1, true, 0, p.s->z1, {{5120, 0, 40}, {120, 20480, 60}});
  for (int i = 0; i < 2; i++) make_map<2>(enc, &maps.z2[i], true, 0, p.s->z2, {{4800, 0, i ? 16u : 24u}, {128, 19200, 128}});
  for (int i = 0; i < 4; i++) make_map<2>(enc, &maps.wf[i], false, 2 - (i & 1), (i & 2) ? p.wi : p.wr, {{16 * DF_, 0, (i & 1) ? 16u : 32u}, {128, 32 * DF_, 128}});
  make_map<2>(enc, &maps.wm, false, 1, p.wmod, {{6 * D_, 0, 16}, {D_, 12 * D_, 192}});
  for (int i = 0; i < 2; i++) make_map<3>(enc, &maps.h3[i], true, 0, p.s->h3, {{1024, 0, 64}, {144, 4096, 18}, {4, 144 * 4096, i ? 4u - H3G : H3G}});
  fused_kernel<<<NCTA, NTHR, SMEM_BYTES, cudaStreamPerThread>>>(p, maps);
}
```

```cpp
#include <cuda_runtime.h>
#include <cuda_bf16.h>
#include <cuda.h>
#include <stdint.h>

namespace {

constexpr int S_ = 2048, D_ = 576, DF_ = 289, F_ = 4608;
constexpr int NCTA = 132, NTHR = 384;
constexpr int STAGE = 36864, NST = 6;
constexpr int STAGE2 = 34816, O_U1 = NST * STAGE2, SMEM_BYTES = 232448;
constexpr uint32_t sbase = 1024, red = sbase + NST * STAGE, full0 = sbase + SMEM_BYTES - 256, empty0 = full0 + 8 * NST;
constexpr int O_NRM = 0, O_B1 = 19456, O_Z1 = 38912, O_P2 = 59392, O_ST = 3 * STAGE;
constexpr int O_RAW = 4 * STAGE;
constexpr int O_IN = 4 * STAGE, O_Y = O_IN + 19456, O_B3 = O_IN + 38912, O_MOD = O_IN + 57344;

__device__ __align__(128) const uint32_t T_TAB[5632] = {
0x3f803f80,0xbf803f80,0x3f803f80,0xbf803f80,0x3f803f80,0xbf803f80,0x3f803f80,0xbf803f80,0x3f803f80,0xbf803f80,0x3f803f80,0xbf803f80,
0x3f803f80,0xbf803f80,0x3f803f80,0xbf803f80,0x3f7f3f80,0xbdc90000,0x3f223f35,0xbf46bf35,0x3f753f7b,0xbe95be48,0x3ef13f0e,0xbf62bf55,
0x3f623f6d,0xbef1bec4,0x3e953ec4,0xbf75bf6d,0x3f463f55,0xbf22bf0e,0x3dc93e48,0xbf7fbf7b,0x3f7b3f80,0xbe480000,0xbe480000,0xbf7bbf80,
0x3f553f6d,0xbf0ebec4,0xbf0ebec4,0xbf55bf6d,0x3f0e3f35,0xbf55bf35,0xbf55bf35,0xbf0ebf35,0x3e483ec4,0xbf7bbf6d,0xbf7bbf6d,0xbe48bec4,
0x3f753f80,0xbe950000,0xbf62bf35,0xbef1bf35,0x3f223f55,0xbf46bf0e,0xbf7fbf7b,0x3dc9be48,0x3dc93ec4,0xbf7fbf6d,0xbf46bf6d,0x3f223ec4,
0xbef1be48,0xbf62bf7b,0xbe95bf0e,0x3f753f55,0x3f6d3f80,0xbec40000,0xbf6dbf80,0x3ec40000,0x3ec43f35,0xbf6dbf35,0xbec4bf35,0x3f6d3f35,
0xbec40000,0xbf6dbf80,0x3ec40000,0x3f6d3f80,0xbf6dbf35,0xbec4bf35,0x3f6d3f35,0x3ec43f35,0x3f623f80,0xbef10000,0xbe95bf35,0x3f753f35,
0x3dc93f0e,0xbf7fbf55,0x3f223e48,0x3f463f7b,0xbf46bec4,0xbf22bf6d,0x3f7f3f6d,0xbdc93ec4,0xbf75bf7b,0x3e95be48,0x3ef13f55,0xbf62bf0e,
0x3f553f80,0xbf0e0000,0x3f0e0000,0x3f553f80,0xbe483ec4,0xbf7bbf6d,0x3f7b3f6d,0xbe483ec4,0xbf7bbf35,0xbe48bf35,0x3e483f35,0xbf7bbf35,
0xbf0ebf6d,0x3f553ec4,0xbf55bec4,0xbf0ebf6d,0x3f463f80,0xbf220000,0x3f7f3f35,0x3dc93f35,0xbef13e48,0xbf62bf7b,0x3e953f55,0xbf75bf0e,
0xbf75bf6d,0x3e95bec4,0xbf62bec4,0xbef1bf6d,0x3dc9bf0e,0x3f7f3f55,0xbf22bf7b,0x3f463e48,0x3f353f80,0xbf350000,0x3f353f80,0xbf350000,
0xbf350000,0xbf35bf80,0xbf350000,0xbf35bf80,0xbf35bf80,0x3f350000,0xbf35bf80,0x3f350000,0x3f350000,0x3f353f80,0x3f350000,0x3f353f80,
0x3f223f80,0xbf460000,0xbdc93f35,0xbf7fbf35,0xbf62be48,0xbef1bf7b,0xbf75bf55,0x3e95bf0e,0xbe95bf6d,0x3f753ec4,0x3ef1bec4,0x3f623f6d,
0x3f7f3f0e,0x3dc93f55,0x3f463f7b,0xbf223e48,0x3f0e3f80,0xbf550000,0xbf550000,0xbf0ebf80,0xbf7bbec4,0xbe48bf6d,0xbe48bf6d,0x3f7b3ec4,
0x3e48bf35,0x3f7b3f35,0x3f7b3f35,0xbe483f35,0x3f553f6d,0xbf0e3ec4,0xbf0e3ec4,0xbf55bf6d,0x3ef13f80,0xbf620000,0xbf75bf35,0x3e95bf35,
0xbf7fbf0e,0x3dc9bf55,0x3f46be48,0x3f223f7b,0x3f22bec4,0x3f463f6d,0x3dc93f6d,0xbf7fbec4,0x3e953f7b,0xbf75be48,0xbf62bf55,0x3ef1bf0e,
0x3ec43f80,0xbf6d0000,0xbec4bf80,0x3f6d0000,0xbf6dbf35,0x3ec4bf35,0x3f6d3f35,0xbec43f35,0x3f6d0000,0x3ec43f80,0xbf6d0000,0xbec4bf80,
0xbec43f35,0xbf6dbf35,0x3ec4bf35,0x3f6d3f35,0x3e953f80,0xbf750000,0x3ef1bf35,0x3f623f35,0xbf46bf55,0x3f22bf0e,0x3dc93f7b,0xbf7fbe48,
0x3f7f3ec4,0xbdc93f6d,0xbf22bf6d,0x3f46bec4,0xbf623e48,0xbef1bf7b,0x3f753f0e,0xbe953f55,0x3e483f80,0xbf7b0000,0x3f7b0000,0x3e483f80,
0xbf0ebf6d,0x3f55bec4,0xbf553ec4,0xbf0ebf6d,0x3f553f35,0xbf0e3f35,0x3f0ebf35,0x3f553f35,0xbf7bbec4,0x3e48bf6d,0xbe483f6d,0xbf7bbec4,
0x3dc93f80,0xbf7f0000,0x3f463f35,0xbf223f35,0xbe95bf7b,0x3f75be48,0xbf62bf0e,0x3ef1bf55,0x3ef13f6d,0xbf623ec4,0x3f753ec4,0xbe953f6d,
0xbf22bf55,0x3f46bf0e,0xbf7fbe48,0x3dc9bf7b,0x3f80,0xbf800000,0x3f80,0xbf800000,0xbf80,0x3f800000,0xbf80,0x3f800000,
0x3f80,0xbf800000,0x3f80,0xbf800000,0xbf80,0x3f800000,0xbf80,0x3f800000,0xbdc93f80,0xbf7f0000,0xbf463f35,0xbf22bf35,
0x3e95bf7b,0x3f753e48,0x3f62bf0e,0x3ef13f55,0xbef13f6d,0xbf62bec4,0xbf753ec4,0xbe95bf6d,0x3f22bf55,0x3f463f0e,0x3f7fbe48,0x3dc93f7b,
0xbe483f80,0xbf7b0000,0xbf7b0000,0x3e48bf80,0x3f0ebf6d,0x3f553ec4,0x3f553ec4,0xbf0e3f6d,0xbf553f35,0xbf0ebf35,0xbf0ebf35,0x3f55bf35,
0x3f7bbec4,0x3e483f6d,0x3e483f6d,0xbf7b3ec4,0xbe953f80,0xbf750000,0xbef1bf35,0x3f62bf35,0x3f46bf55,0x3f223f0e,0xbdc93f7b,0xbf7f3e48,
0xbf7f3ec4,0xbdc9bf6d,0x3f22bf6d,0x3f463ec4,0x3f623e48,0xbef13f7b,0xbf753f0e,0xbe95bf55,0xbec43f80,0xbf6d0000,0x3ec4bf80,0x3f6d0000,
0x3f6dbf35,0x3ec43f35,0xbf6d3f35,0xbec4bf35,0xbf6d0000,0x3ec4bf80,0x3f6d0000,0xbec43f80,0x3ec43f35,0xbf6d3f35,0xbec4bf35,0x3f6dbf35,
0xbef13f80,0xbf620000,0x3f75bf35,0x3e953f35,0x3f7fbf0e,0x3dc93f55,0xbf46be48,0x3f22bf7b,0xbf22bec4,0x3f46bf6d,0xbdc93f6d,0xbf7f3ec4,
0xbe953f7b,0xbf753e48,0x3f62bf55,0x3ef13f0e,0xbf0e3f80,0xbf550000,0x3f550000,0xbf0e3f80,0x3f7bbec4,0xbe483f6d,0x3e48bf6d,0x3f7bbec4,
0xbe48bf35,0x3f7bbf35,0xbf7b3f35,0xbe48bf35,0xbf553f6d,0xbf0ebec4,0x3f0e3ec4,0xbf553f6d,0xbf223f80,0xbf460000,0x3dc93f35,0xbf7f3f35,
0x3f62be48,0xbef13f7b,0x3f75bf55,0x3e953f0e,0x3e95bf6d,0x3f75bec4,0xbef1bec4,0x3f62bf6d,0xbf7f3f0e,0x3dc9bf55,0xbf463f7b,0xbf22be48,
0xbf353f80,0xbf350000,0xbf353f80,0xbf350000,0x3f350000,0xbf353f80,0x3f350000,0xbf353f80,0x3f35bf80,0x3f350000,0x3f35bf80,0x3f350000,
0xbf350000,0x3f35bf80,0xbf350000,0x3f35bf80,0xbf463f80,0xbf220000,0xbf7f3f35,0x3dc9bf35,0x3ef13e48,0xbf623f7b,0xbe953f55,0xbf753f0e,
0x3f75bf6d,0x3e953ec4,0x3f62bec4,0xbef13f6d,0xbdc9bf0e,0x3f7fbf55,0x3f22bf7b,0x3f46be48,0xbf553f80,0xbf0e0000,0xbf0e0000,0x3f55bf80,
0x3e483ec4,0xbf7b3f6d,0xbf7b3f6d,0xbe48bec4,0x3f7bbf35,0xbe483f35,0xbe483f35,0xbf7b3f35,0x3f0ebf6d,0x3f55bec4,0x3f55bec4,0xbf0e3f6d,
0xbf623f80,0xbef10000,0x3e95bf35,0x3f75bf35,0xbdc93f0e,0xbf7f3f55,0xbf223e48,0x3f46bf7b,0x3f46bec4,0xbf223f6d,0xbf7f3f6d,0xbdc9bec4,
0x3f75bf7b,0x3e953e48,0xbef13f55,0xbf623f0e,0xbf6d3f80,0xbec40000,0x3f6dbf80,0x3ec40000,0xbec43f35,0xbf6d3f35,0x3ec4bf35,0x3f6dbf35,
0x3ec40000,0xbf6d3f80,0xbec40000,0x3f6dbf80,0x3f6dbf35,0xbec43f35,0xbf6d3f35,0x3ec4bf35,0xbf753f80,0xbe950000,0x3f62bf35,0xbef13f35,
0xbf223f55,0xbf463f0e,0x3f7fbf7b,0x3dc93e48,0xbdc93ec4,0xbf7f3f6d,0x3f46bf6d,0x3f22bec4,0x3ef1be48,0xbf623f7b,0x3e95bf0e,0x3f75bf55,
0xbf7b3f80,0xbe480000,0x3e480000,0xbf7b3f80,0xbf553f6d,0xbf0e3ec4,0x3f0ebec4,0xbf553f6d,0xbf0e3f35,0xbf553f35,0x3f55bf35,0xbf0e3f35,
0xbe483ec4,0xbf7b3f6d,0x3f7bbf6d,0xbe483ec4,0xbf7f3f80,0xbdc90000,0xbf223f35,0xbf463f35,0xbf753f7b,0xbe953e48,0xbef13f0e,0xbf623f55,
0xbf623f6d,0xbef13ec4,0xbe953ec4,0xbf753f6d,0xbf463f55,0xbf223f0e,0xbdc93e48,0xbf7f3f7b,0x3f803f80,0xbf803f80,0x3f803f80,0xbf803f80,
0x3f803f80,0xbf803f80,0x3f803f80,0xbf803f80,0x3f803f80,0xbf803f80,0x3f803f80,0xbf803f80,0x3f803f80,0xbf803f80,0x3f803f80,0xbf803f80,
0xbdc90000,0xbf7fbf80,0xbf46bf35,0xbf22bf35,0xbe95be48,0xbf75bf7b,0xbf62bf55,0xbef1bf0e,0xbef1bec4,0xbf62bf6d,0xbf75bf6d,0xbe95bec4,
0xbf22bf0e,0xbf46bf55,0xbf7fbf7b,0xbdc9be48,0xbf7bbf80,0x3e480000,0x3e480000,0x3f7b3f80,0xbf55bf6d,0x3f0e3ec4,0x3f0e3ec4,0x3f553f6d,
0xbf0ebf35,0x3f553f35,0x3f553f35,0x3f0e3f35,0xbe48bec4,0x3f7b3f6d,0x3f7b3f6d,0x3e483ec4,0x3e950000,0x3f753f80,0x3ef13f35,0xbf62bf35,
0x3f463f0e,0x3f223f55,0xbdc93e48,0xbf7fbf7b,0x3f7f3f6d,0x3dc93ec4,0xbf22bec4,0xbf46bf6d,0x3f623f7b,0xbef1be48,0xbf75bf55,0xbe95bf0e,
0x3f6d3f80,0xbec40000,0xbf6dbf80,0x3ec40000,0x3ec43f35,0xbf6dbf35,0xbec4bf35,0x3f6d3f35,0xbec40000,0xbf6dbf80,0x3ec40000,0x3f6d3f80,
0xbf6dbf35,0xbec4bf35,0x3f6d3f35,0x3ec43f35,0xbef10000,0xbf62bf80,0x3f753f35,0x3e953f35,0xbf7fbf55,0xbdc9bf0e,0x3f463f7b,0xbf22be48,
0xbf22bf6d,0x3f463ec4,0xbdc93ec4,0xbf7fbf6d,0x3e95be48,0x3f753f7b,0xbf62bf0e,0xbef1bf55,0xbf55bf80,0x3f0e0000,0xbf0e0000,0xbf55bf80,
0x3e48bec4,0x3f7b3f6d,0xbf7bbf6d,0x3e48bec4,0x3f7b3f35,0x3e483f35,0xbe48bf35,0x3f7b3f35,0x3f0e3f6d,0xbf55bec4,0x3f553ec4,0x3f0e3f6d,
0x3f220000,0x3f463f80,0xbdc9bf35,0x3f7f3f35,0x3f623f7b,0xbef13e48,0x3f753f0e,0x3e953f55,0xbe953ec4,0xbf75bf6d,0x3ef13f6d,0xbf62bec4,
0xbf7fbf55,0x3dc9bf0e,0xbf46be48,0xbf22bf7b,0x3f353f80,0xbf350000,0x3f353f80,0xbf350000,0xbf350000,0xbf35bf80,0xbf350000,0xbf35bf80,
0xbf35bf80,0x3f350000,0xbf35bf80,0x3f350000,0x3f350000,0x3f353f80,0x3f350000,0x3f353f80,0xbf460000,0xbf22bf80,0xbf7fbf35,0x3dc9bf35,
0xbef1bf7b,0x3f623e48,0x3e95bf0e,0x3f753f55,0x3f753ec4,0x3e953f6d,0x3f623f6d,0xbef13ec4,0x3dc93f55,0xbf7fbf0e,0xbf223e48,0xbf46bf7b,
0xbf0ebf80,0x3f550000,0x3f550000,0x3f0e3f80,0x3f7b3ec4,0x3e483f6d,0x3e483f6d,0xbf7bbec4,0xbe483f35,0xbf7bbf35,0xbf7bbf35,0x3e48bf35,
0xbf55bf6d,0x3f0ebec4,0x3f0ebec4,0x3f553f6d,0x3f620000,0x3ef13f80,0xbe953f35,0xbf75bf35,0xbdc93f55,0xbf7fbf0e,0xbf22bf7b,0x3f46be48,
0xbf46bf6d,0x3f22bec4,0x3f7f3ec4,0x3dc93f6d,0x3f753e48,0x3e953f7b,0xbef13f0e,0xbf62bf55,0x3ec43f80,0xbf6d0000,0xbec4bf80,0x3f6d0000,
0xbf6dbf35,0x3ec4bf35,0x3f6d3f35,0xbec43f35,0x3f6d0000,0x3ec43f80,0xbf6d0000,0xbec4bf80,0xbec43f35,0xbf6dbf35,0x3ec4bf35,0x3f6d3f35,
0xbf750000,0xbe95bf80,0x3f623f35,0xbef13f35,0x3f22bf0e,0x3f463f55,0xbf7fbe48,0xbdc9bf7b,0xbdc93f6d,0xbf7fbec4,0x3f46bec4,0x3f223f6d,
0xbef1bf7b,0x3f62be48,0xbe953f55,0xbf75bf0e,0xbe48bf80,0x3f7b0000,0xbf7b0000,0xbe48bf80,0x3f0e3f6d,0xbf553ec4,0x3f55bec4,0x3f0e3f6d,
0xbf55bf35,0x3f0ebf35,0xbf0e3f35,0xbf55bf35,0x3f7b3ec4,0xbe483f6d,0x3e48bf6d,0x3f7b3ec4,0x3f7f0000,0x3dc93f80,0x3f22bf35,0x3f463f35,
0xbf753e48,0xbe95bf7b,0xbef13f55,0xbf62bf0e,0x3f62bec4,0x3ef13f6d,0x3e95bf6d,0x3f753ec4,0xbf463f0e,0xbf22bf55,0xbdc93f7b,0xbf7fbe48,
0x3f80,0xbf800000,0x3f80,0xbf800000,0xbf80,0x3f800000,0xbf80,0x3f800000,0x3f80,0xbf800000,0x3f80,0xbf800000,
0xbf80,0x3f800000,0xbf80,0x3f800000,0xbf7f0000,0x3dc9bf80,0xbf22bf35,0x3f46bf35,0x3f753e48,0xbe953f7b,0x3ef13f55,0xbf623f0e,
0xbf62bec4,0x3ef1bf6d,0xbe95bf6d,0x3f75bec4,0x3f463f0e,0xbf223f55,0x3dc93f7b,0xbf7f3e48,0x3e48bf80,0x3f7b0000,0x3f7b0000,0xbe483f80,
0xbf0e3f6d,0xbf55bec4,0xbf55bec4,0x3f0ebf6d,0x3f55bf35,0x3f0e3f35,0x3f0e3f35,0xbf553f35,0xbf7b3ec4,0xbe48bf6d,0xbe48bf6d,0x3f7bbec4,
0x3f750000,0xbe953f80,0xbf623f35,0xbef1bf35,0xbf22bf0e,0x3f46bf55,0x3f7fbe48,0xbdc93f7b,0x3dc93f6d,0xbf7f3ec4,0xbf46bec4,0x3f22bf6d,
0x3ef1bf7b,0x3f623e48,0x3e953f55,0xbf753f0e,0xbec43f80,0xbf6d0000,0x3ec4bf80,0x3f6d0000,0x3f6dbf35,0x3ec43f35,0xbf6d3f35,0xbec4bf35,
0xbf6d0000,0x3ec4bf80,0x3f6d0000,0xbec43f80,0x3ec43f35,0xbf6d3f35,0xbec4bf35,0x3f6dbf35,0xbf620000,0x3ef1bf80,0x3e953f35,0xbf753f35,
0x3dc93f55,0xbf7f3f0e,0x3f22bf7b,0x3f463e48,0x3f46bf6d,0x3f223ec4,0xbf7f3ec4,0x3dc9bf6d,0xbf753e48,0x3e95bf7b,0x3ef13f0e,0xbf623f55,
0x3f0ebf80,0x3f550000,0xbf550000,0x3f0ebf80,0xbf7b3ec4,0x3e48bf6d,0xbe483f6d,0xbf7b3ec4,0x3e483f35,0xbf7b3f35,0x3f7bbf35,0x3e483f35,
0x3f55bf6d,0x3f0e3ec4,0xbf0ebec4,0x3f55bf6d,0x3f460000,0xbf223f80,0x3f7fbf35,0x3dc93f35,0x3ef1bf7b,0x3f62be48,0xbe95bf0e,0x3f75bf55,
0xbf753ec4,0x3e95bf6d,0xbf623f6d,0xbef1bec4,0xbdc93f55,0xbf7f3f0e,0x3f223e48,0xbf463f7b,0xbf353f80,0xbf350000,0xbf353f80,0xbf350000,
0x3f350000,0xbf353f80,0x3f350000,0xbf353f80,0x3f35bf80,0x3f350000,0x3f35bf80,0x3f350000,0xbf350000,0x3f35bf80,0xbf350000,0x3f35bf80,
0xbf220000,0x3f46bf80,0x3dc9bf35,0x3f7fbf35,0xbf623f7b,0xbef1be48,0xbf753f0e,0x3e95bf55,0x3e953ec4,0xbf753f6d,0xbef13f6d,0xbf623ec4,
0x3f7fbf55,0x3dc93f0e,0x3f46be48,0xbf223f7b,0x3f55bf80,0x3f0e0000,0x3f0e0000,0xbf553f80,0xbe48bec4,0x3f7bbf6d,0x3f7bbf6d,0x3e483ec4,
0xbf7b3f35,0x3e48bf35,0x3e48bf35,0x3f7bbf35,0xbf0e3f6d,0xbf553ec4,0xbf553ec4,0x3f0ebf6d,0x3ef10000,0xbf623f80,0xbf753f35,0x3e95bf35,
0x3f7fbf55,0xbdc93f0e,0xbf463f7b,0xbf223e48,0x3f22bf6d,0x3f46bec4,0x3dc93ec4,0xbf7f3f6d,0xbe95be48,0x3f75bf7b,0x3f62bf0e,0xbef13f55,
0xbf6d3f80,0xbec40000,0x3f6dbf80,0x3ec40000,0xbec43f35,0xbf6d3f35,0x3ec4bf35,0x3f6dbf35,0x3ec40000,0xbf6d3f80,0xbec40000,0x3f6dbf80,
0x3f6dbf35,0xbec43f35,0xbf6d3f35,0x3ec4bf35,0xbe950000,0x3f75bf80,0xbef13f35,0xbf623f35,0xbf463f0e,0x3f22bf55,0x3dc93e48,0xbf7f3f7b,
0xbf7f3f6d,0x3dc9bec4,0x3f22bec4,0xbf463f6d,0xbf623f7b,0xbef13e48,0x3f75bf55,0xbe953f0e,0x3f7bbf80,0x3e480000,0xbe480000,0x3f7bbf80,
0x3f55bf6d,0x3f0ebec4,0xbf0e3ec4,0x3f55bf6d,0x3f0ebf35,0x3f55bf35,0xbf553f35,0x3f0ebf35,0x3e48bec4,0x3f7bbf6d,0xbf7b3f6d,0x3e48bec4,
0x3dc90000,0xbf7f3f80,0x3f46bf35,0xbf223f35,0x3e95be48,0xbf753f7b,0x3f62bf55,0xbef13f0e,0x3ef1bec4,0xbf623f6d,0x3f75bf6d,0xbe953ec4,
0x3f22bf0e,0xbf463f55,0x3f7fbf7b,0xbdc93e48,0x3f803f80,0xbf803f80,0x3f803f80,0xbf803f80,0x3f803f80,0xbf803f80,0x3f803f80,0xbf803f80,
0x3f803f80,0xbf803f80,0x3f803f80,0xbf803f80,0x3f803f80,0xbf803f80,0x3f803f80,0xbf803f80,0xbf7fbf80,0x3dc90000,0xbf22bf35,0x3f463f35,
0xbf75bf7b,0x3e953e48,0xbef1bf0e,0x3f623f55,0xbf62bf6d,0x3ef13ec4,0xbe95bec4,0x3f753f6d,0xbf46bf55,0x3f223f0e,0xbdc9be48,0x3f7f3f7b,
0x3f7b3f80,0xbe480000,0xbe480000,0xbf7bbf80,0x3f553f6d,0xbf0ebec4,0xbf0ebec4,0xbf55bf6d,0x3f0e3f35,0xbf55bf35,0xbf55bf35,0xbf0ebf35,
0x3e483ec4,0xbf7bbf6d,0xbf7bbf6d,0xbe48bec4,0xbf75bf80,0x3e950000,0x3f623f35,0x3ef13f35,0xbf22bf55,0x3f463f0e,0x3f7f3f7b,0xbdc93e48,
0xbdc9bec4,0x3f7f3f6d,0x3f463f6d,0xbf22bec4,0x3ef13e48,0x3f623f7b,0x3e953f0e,0xbf75bf55,0x3f6d3f80,0xbec40000,0xbf6dbf80,0x3ec40000,
0x3ec43f35,0xbf6dbf35,0xbec4bf35,0x3f6d3f35,0xbec40000,0xbf6dbf80,0x3ec40000,0x3f6d3f80,0xbf6dbf35,0xbec4bf35,0x3f6d3f35,0x3ec43f35,
0xbf62bf80,0x3ef10000,0x3e953f35,0xbf75bf35,0xbdc9bf0e,0x3f7f3f55,0xbf22be48,0xbf46bf7b,0x3f463ec4,0x3f223f6d,0xbf7fbf6d,0x3dc9bec4,
0x3f753f7b,0xbe953e48,0xbef1bf55,0x3f623f0e,0x3f553f80,0xbf0e0000,0x3f0e0000,0x3f553f80,0xbe483ec4,0xbf7bbf6d,0x3f7b3f6d,0xbe483ec4,
0xbf7bbf35,0xbe48bf35,0x3e483f35,0xbf7bbf35,0xbf0ebf6d,0x3f553ec4,0xbf55bec4,0xbf0ebf6d,0xbf46bf80,0x3f220000,0xbf7fbf35,0xbdc9bf35,
0x3ef1be48,0x3f623f7b,0xbe95bf55,0x3f753f0e,0x3f753f6d,0xbe953ec4,0x3f623ec4,0x3ef13f6d,0xbdc93f0e,0xbf7fbf55,0x3f223f7b,0xbf46be48,
0x3f353f80,0xbf350000,0x3f353f80,0xbf350000,0xbf350000,0xbf35bf80,0xbf350000,0xbf35bf80,0xbf35bf80,0x3f350000,0xbf35bf80,0x3f350000,
0x3f350000,0x3f353f80,0x3f350000,0x3f353f80,0xbf22bf80,0x3f460000,0x3dc9bf35,0x3f7f3f35,0x3f623e48,0x3ef13f7b,0x3f753f55,0xbe953f0e,
0x3e953f6d,0xbf75bec4,0xbef13ec4,0xbf62bf6d,0xbf7fbf0e,0xbdc9bf55,0xbf46bf7b,0x3f22be48,0x3f0e3f80,0xbf550000,0xbf550000,0xbf0ebf80,
0xbf7bbec4,0xbe48bf6d,0xbe48bf6d,0x3f7b3ec4,0x3e48bf35,0x3f7b3f35,0x3f7b3f35,0xbe483f35,0x3f553f6d,0xbf0e3ec4,0xbf0e3ec4,0xbf55bf6d,
0xbef1bf80,0x3f620000,0x3f753f35,0xbe953f35,0x3f7f3f0e,0xbdc93f55,0xbf463e48,0xbf22bf7b,0xbf223ec4,0xbf46bf6d,0xbdc9bf6d,0x3f7f3ec4,
0xbe95bf7b,0x3f753e48,0x3f623f55,0xbef13f0e,0x3ec43f80,0xbf6d0000,0xbec4bf80,0x3f6d0000,0xbf6dbf35,0x3ec4bf35,0x3f6d3f35,0xbec43f35,
0x3f6d0000,0x3ec43f80,0xbf6d0000,0xbec4bf80,0xbec43f35,0xbf6dbf35,0x3ec4bf35,0x3f6d3f35,0xbe95bf80,0x3f750000,0xbef13f35,0xbf62bf35,
0x3f463f55,0xbf223f0e,0xbdc9bf7b,0x3f7f3e48,0xbf7fbec4,0x3dc9bf6d,0x3f223f6d,0xbf463ec4,0x3f62be48,0x3ef13f7b,0xbf75bf0e,0x3e95bf55,
0x3e483f80,0xbf7b0000,0x3f7b0000,0x3e483f80,0xbf0ebf6d,0x3f55bec4,0xbf553ec4,0xbf0ebf6d,0x3f553f35,0xbf0e3f35,0x3f0ebf35,0x3f553f35,
0xbf7bbec4,0x3e48bf6d,0xbe483f6d,0xbf7bbec4,0xbdc9bf80,0x3f7f0000,0xbf46bf35,0x3f22bf35,0x3e953f7b,0xbf753e48,0x3f623f0e,0xbef13f55,
0xbef1bf6d,0x3f62bec4,0xbf75bec4,0x3e95bf6d,0x3f223f55,0xbf463f0e,0x3f7f3e48,0xbdc93f7b,0x3f80,0xbf800000,0x3f80,0xbf800000,
0xbf80,0x3f800000,0xbf80,0x3f800000,0x3f80,0xbf800000,0x3f80,0xbf800000,0xbf80,0x3f800000,0xbf80,0x3f800000,
0x3dc9bf80,0x3f7f0000,0x3f46bf35,0x3f223f35,0xbe953f7b,0xbf75be48,0xbf623f0e,0xbef1bf55,0x3ef1bf6d,0x3f623ec4,0x3f75bec4,0x3e953f6d,
0xbf223f55,0xbf46bf0e,0xbf7f3e48,0xbdc9bf7b,0xbe483f80,0xbf7b0000,0xbf7b0000,0x3e48bf80,0x3f0ebf6d,0x3f553ec4,0x3f553ec4,0xbf0e3f6d,
0xbf553f35,0xbf0ebf35,0xbf0ebf35,0x3f55bf35,0x3f7bbec4,0x3e483f6d,0x3e483f6d,0xbf7b3ec4,0x3e95bf80,0x3f750000,0x3ef13f35,0xbf623f35,
0xbf463f55,0xbf22bf0e,0x3dc9bf7b,0x3f7fbe48,0x3f7fbec4,0x3dc93f6d,0xbf223f6d,0xbf46bec4,0xbf62be48,0x3ef1bf7b,0x3f75bf0e,0x3e953f55,
0xbec43f80,0xbf6d0000,0x3ec4bf80,0x3f6d0000,0x3f6dbf35,0x3ec43f35,0xbf6d3f35,0xbec4bf35,0xbf6d0000,0x3ec4bf80,0x3f6d0000,0xbec43f80,
0x3ec43f35,0xbf6d3f35,0xbec4bf35,0x3f6dbf35,0x3ef1bf80,0x3f620000,0xbf753f35,0xbe95bf35,0xbf7f3f0e,0xbdc9bf55,0x3f463e48,0xbf223f7b,
0x3f223ec4,0xbf463f6d,0x3dc9bf6d,0x3f7fbec4,0x3e95bf7b,0x3f75be48,0xbf623f55,0xbef1bf0e,0xbf0e3f80,0xbf550000,0x3f550000,0xbf0e3f80,
0x3f7bbec4,0xbe483f6d,0x3e48bf6d,0x3f7bbec4,0xbe48bf35,0x3f7bbf35,0xbf7b3f35,0xbe48bf35,0xbf553f6d,0xbf0ebec4,0x3f0e3ec4,0xbf553f6d,
0x3f22bf80,0x3f460000,0xbdc9bf35,0x3f7fbf35,0xbf623e48,0x3ef1bf7b,0xbf753f55,0xbe95bf0e,0xbe953f6d,0xbf753ec4,0x3ef13ec4,0xbf623f6d,
0x3f7fbf0e,0xbdc93f55,0x3f46bf7b,0x3f223e48,0xbf353f80,0xbf350000,0xbf353f80,0xbf350000,0x3f350000,0xbf353f80,0x3f350000,0xbf353f80,
0x3f35bf80,0x3f350000,0x3f35bf80,0x3f350000,0xbf350000,0x3f35bf80,0xbf350000,0x3f35bf80,0x3f46bf80,0x3f220000,0x3f7fbf35,0xbdc93f35,
0xbef1be48,0x3f62bf7b,0x3e95bf55,0x3f75bf0e,0xbf753f6d,0xbe95bec4,0xbf623ec4,0x3ef1bf6d,0x3dc93f0e,0xbf7f3f55,0xbf223f7b,0xbf463e48,
0xbf553f80,0xbf0e0000,0xbf0e0000,0x3f55bf80,0x3e483ec4,0xbf7b3f6d,0xbf7b3f6d,0xbe48bec4,0x3f7bbf35,0xbe483f35,0xbe483f35,0xbf7b3f35,
0x3f0ebf6d,0x3f55bec4,0x3f55bec4,0xbf0e3f6d,0x3f62bf80,0x3ef10000,0xbe953f35,0xbf753f35,0x3dc9bf0e,0x3f7fbf55,0x3f22be48,0xbf463f7b,
0xbf463ec4,0x3f22bf6d,0x3f7fbf6d,0x3dc93ec4,0xbf753f7b,0xbe95be48,0x3ef1bf55,0x3f62bf0e,0xbf6d3f80,0xbec40000,0x3f6dbf80,0x3ec40000,
0xbec43f35,0xbf6d3f35,0x3ec4bf35,0x3f6dbf35,0x3ec40000,0xbf6d3f80,0xbec40000,0x3f6dbf80,0x3f6dbf35,0xbec43f35,0xbf6d3f35,0x3ec4bf35,
0x3f75bf80,0x3e950000,0xbf623f35,0x3ef1bf35,0x3f22bf55,0x3f46bf0e,0xbf7f3f7b,0xbdc9be48,0x3dc9bec4,0x3f7fbf6d,0xbf463f6d,0xbf223ec4,
0xbef13e48,0x3f62bf7b,0xbe953f0e,0xbf753f55,0xbf7b3f80,0xbe480000,0x3e480000,0xbf7b3f80,0xbf553f6d,0xbf0e3ec4,0x3f0ebec4,0xbf553f6d,
0xbf0e3f35,0xbf553f35,0x3f55bf35,0xbf0e3f35,0xbe483ec4,0xbf7b3f6d,0x3f7bbf6d,0xbe483ec4,0x3f7fbf80,0x3dc90000,0x3f22bf35,0x3f46bf35,
0x3f75bf7b,0x3e95be48,0x3ef1bf0e,0x3f62bf55,0x3f62bf6d,0x3ef1bec4,0x3e95bec4,0x3f75bf6d,0x3f46bf55,0x3f22bf0e,0x3dc9be48,0x3f7fbf7b,
0x3f803f80,0xbf803f80,0x3f803f80,0xbf803f80,0x3f803f80,0xbf803f80,0x3f803f80,0xbf803f80,0x3f803f80,0xbf803f80,0x3f803f80,0xbf803f80,
0x3f803f80,0xbf803f80,0x3f803f80,0xbf803f80,0x3dc90000,0x3f7f3f80,0x3f463f35,0x3f223f35,0x3e953e48,0x3f753f7b,0x3f623f55,0x3ef13f0e,
0x3ef13ec4,0x3f623f6d,0x3f753f6d,0x3e953ec4,0x3f223f0e,0x3f463f55,0x3f7f3f7b,0x3dc93e48,0xbf7bbf80,0x3e480000,0x3e480000,0x3f7b3f80,
0xbf55bf6d,0x3f0e3ec4,0x3f0e3ec4,0x3f553f6d,0xbf0ebf35,0x3f553f35,0x3f553f35,0x3f0e3f35,0xbe48bec4,0x3f7b3f6d,0x3f7b3f6d,0x3e483ec4,
0xbe950000,0xbf75bf80,0xbef1bf35,0x3f623f35,0xbf46bf0e,0xbf22bf55,0x3dc9be48,0x3f7f3f7b,0xbf7fbf6d,0xbdc9bec4,0x3f223ec4,0x3f463f6d,
0xbf62bf7b,0x3ef13e48,0x3f753f55,0x3e953f0e,0x3f6d3f80,0xbec40000,0xbf6dbf80,0x3ec40000,0x3ec43f35,0xbf6dbf35,0xbec4bf35,0x3f6d3f35,
0xbec40000,0xbf6dbf80,0x3ec40000,0x3f6d3f80,0xbf6dbf35,0xbec4bf35,0x3f6d3f35,0x3ec43f35,0x3ef10000,0x3f623f80,0xbf75bf35,0xbe95bf35,
0x3f7f3f55,0x3dc93f0e,0xbf46bf7b,0x3f223e48,0x3f223f6d,0xbf46bec4,0x3dc9bec4,0x3f7f3f6d,0xbe953e48,0xbf75bf7b,0x3f623f0e,0x3ef13f55,
0xbf55bf80,0x3f0e0000,0xbf0e0000,0xbf55bf80,0x3e48bec4,0x3f7b3f6d,0xbf7bbf6d,0x3e48bec4,0x3f7b3f35,0x3e483f35,0xbe48bf35,0x3f7b3f35,
0x3f0e3f6d,0xbf55bec4,0x3f553ec4,0x3f0e3f6d,0xbf220000,0xbf46bf80,0x3dc93f35,0xbf7fbf35,0xbf62bf7b,0x3ef1be48,0xbf75bf0e,0xbe95bf55,
0x3e95bec4,0x3f753f6d,0xbef1bf6d,0x3f623ec4,0x3f7f3f55,0xbdc93f0e,0x3f463e48,0x3f223f7b,0x3f353f80,0xbf350000,0x3f353f80,0xbf350000,
0xbf350000,0xbf35bf80,0xbf350000,0xbf35bf80,0xbf35bf80,0x3f350000,0xbf35bf80,0x3f350000,0x3f350000,0x3f353f80,0x3f350000,0x3f353f80,
0x3f460000,0x3f223f80,0x3f7f3f35,0xbdc93f35,0x3ef13f7b,0xbf62be48,0xbe953f0e,0xbf75bf55,0xbf75bec4,0xbe95bf6d,0xbf62bf6d,0x3ef1bec4,
0xbdc9bf55,0x3f7f3f0e,0x3f22be48,0x3f463f7b,0xbf0ebf80,0x3f550000,0x3f550000,0x3f0e3f80,0x3f7b3ec4,0x3e483f6d,0x3e483f6d,0xbf7bbec4,
0xbe483f35,0xbf7bbf35,0xbf7bbf35,0x3e48bf35,0xbf55bf6d,0x3f0ebec4,0x3f0ebec4,0x3f553f6d,0xbf620000,0xbef1bf80,0x3e95bf35,0x3f753f35,
0x3dc9bf55,0x3f7f3f0e,0x3f223f7b,0xbf463e48,0x3f463f6d,0xbf223ec4,0xbf7fbec4,0xbdc9bf6d,0xbf75be48,0xbe95bf7b,0x3ef1bf0e,0x3f623f55,
0x3ec43f80,0xbf6d0000,0xbec4bf80,0x3f6d0000,0xbf6dbf35,0x3ec4bf35,0x3f6d3f35,0xbec43f35,0x3f6d0000,0x3ec43f80,0xbf6d0000,0xbec4bf80,
0xbec43f35,0xbf6dbf35,0x3ec4bf35,0x3f6d3f35,0x3f750000,0x3e953f80,0xbf62bf35,0x3ef1bf35,0xbf223f0e,0xbf46bf55,0x3f7f3e48,0x3dc93f7b,
0x3dc9bf6d,0x3f7f3ec4,0xbf463ec4,0xbf22bf6d,0x3ef13f7b,0xbf623e48,0x3e95bf55,0x3f753f0e,0xbe48bf80,0x3f7b0000,0xbf7b0000,0xbe48bf80,
0x3f0e3f6d,0xbf553ec4,0x3f55bec4,0x3f0e3f6d,0xbf55bf35,0x3f0ebf35,0xbf0e3f35,0xbf55bf35,0x3f7b3ec4,0xbe483f6d,0x3e48bf6d,0x3f7b3ec4,
0xbf7f0000,0xbdc9bf80,0xbf223f35,0xbf46bf35,0x3f75be48,0x3e953f7b,0x3ef1bf55,0x3f623f0e,0xbf623ec4,0xbef1bf6d,0xbe953f6d,0xbf75bec4,
0x3f46bf0e,0x3f223f55,0x3dc9bf7b,0x3f7f3e48,0x3f80,0xbf800000,0x3f80,0xbf800000,0xbf80,0x3f800000,0xbf80,0x3f800000,
0x3f80,0xbf800000,0x3f80,0xbf800000,0xbf80,0x3f800000,0xbf80,0x3f800000,0x3f7f0000,0xbdc93f80,0x3f223f35,0xbf463f35,
0xbf75be48,0x3e95bf7b,0xbef1bf55,0x3f62bf0e,0x3f623ec4,0xbef13f6d,0x3e953f6d,0xbf753ec4,0xbf46bf0e,0x3f22bf55,0xbdc9bf7b,0x3f7fbe48,
0x3e48bf80,0x3f7b0000,0x3f7b0000,0xbe483f80,0xbf0e3f6d,0xbf55bec4,0xbf55bec4,0x3f0ebf6d,0x3f55bf35,0x3f0e3f35,0x3f0e3f35,0xbf553f35,
0xbf7b3ec4,0xbe48bf6d,0xbe48bf6d,0x3f7bbec4,0xbf750000,0x3e95bf80,0x3f62bf35,0x3ef13f35,0x3f223f0e,0xbf463f55,0xbf7f3e48,0x3dc9bf7b,
0xbdc9bf6d,0x3f7fbec4,0x3f463ec4,0xbf223f6d,0xbef13f7b,0xbf62be48,0xbe95bf55,0x3f75bf0e,0xbec43f80,0xbf6d0000,0x3ec4bf80,0x3f6d0000,
0x3f6dbf35,0x3ec43f35,0xbf6d3f35,0xbec4bf35,0xbf6d0000,0x3ec4bf80,0x3f6d0000,0xbec43f80,0x3ec43f35,0xbf6d3f35,0xbec4bf35,0x3f6dbf35,
0x3f620000,0xbef13f80,0xbe95bf35,0x3f75bf35,0xbdc9bf55,0x3f7fbf0e,0xbf223f7b,0xbf46be48,0xbf463f6d,0xbf22bec4,0x3f7fbec4,0xbdc93f6d,
0x3f75be48,0xbe953f7b,0xbef1bf0e,0x3f62bf55,0x3f0ebf80,0x3f550000,0xbf550000,0x3f0ebf80,0xbf7b3ec4,0x3e48bf6d,0xbe483f6d,0xbf7b3ec4,
0x3e483f35,0xbf7b3f35,0x3f7bbf35,0x3e483f35,0x3f55bf6d,0x3f0e3ec4,0xbf0ebec4,0x3f55bf6d,0xbf460000,0x3f22bf80,0xbf7f3f35,0xbdc9bf35,
0xbef13f7b,0xbf623e48,0x3e953f0e,0xbf753f55,0x3f75bec4,0xbe953f6d,0x3f62bf6d,0x3ef13ec4,0x3dc9bf55,0x3f7fbf0e,0xbf22be48,0x3f46bf7b,
0xbf353f80,0xbf350000,0xbf353f80,0xbf350000,0x3f350000,0xbf353f80,0x3f350000,0xbf353f80,0x3f35bf80,0x3f350000,0x3f35bf80,0x3f350000,
0xbf350000,0x3f35bf80,0xbf350000,0x3f35bf80,0x3f220000,0xbf463f80,0xbdc93f35,0xbf7f3f35,0x3f62bf7b,0x3ef13e48,0x3f75bf0e,0xbe953f55,
0xbe95bec4,0x3f75bf6d,0x3ef1bf6d,0x3f62bec4,0xbf7f3f55,0xbdc9bf0e,0xbf463e48,0x3f22bf7b,0x3f55bf80,0x3f0e0000,0x3f0e0000,0xbf553f80,
0xbe48bec4,0x3f7bbf6d,0x3f7bbf6d,0x3e483ec4,0xbf7b3f35,0x3e48bf35,0x3e48bf35,0x3f7bbf35,0xbf0e3f6d,0xbf553ec4,0xbf553ec4,0x3f0ebf6d,
0xbef10000,0x3f62bf80,0x3f75bf35,0xbe953f35,0xbf7f3f55,0x3dc9bf0e,0x3f46bf7b,0x3f22be48,0xbf223f6d,0xbf463ec4,0xbdc9bec4,0x3f7fbf6d,
0x3e953e48,0xbf753f7b,0xbf623f0e,0x3ef1bf55,0xbf6d3f80,0xbec40000,0x3f6dbf80,0x3ec40000,0xbec43f35,0xbf6d3f35,0x3ec4bf35,0x3f6dbf35,
0x3ec40000,0xbf6d3f80,0xbec40000,0x3f6dbf80,0x3f6dbf35,0xbec43f35,0xbf6d3f35,0x3ec4bf35,0x3e950000,0xbf753f80,0x3ef1bf35,0x3f62bf35,
0x3f46bf0e,0xbf223f55,0xbdc9be48,0x3f7fbf7b,0x3f7fbf6d,0xbdc93ec4,0xbf223ec4,0x3f46bf6d,0x3f62bf7b,0x3ef1be48,0xbf753f55,0x3e95bf0e,
0x3f7bbf80,0x3e480000,0xbe480000,0x3f7bbf80,0x3f55bf6d,0x3f0ebec4,0xbf0e3ec4,0x3f55bf6d,0x3f0ebf35,0x3f55bf35,0xbf553f35,0x3f0ebf35,
0x3e48bec4,0x3f7bbf6d,0xbf7b3f6d,0x3e48bec4,0xbdc90000,0x3f7fbf80,0xbf463f35,0x3f22bf35,0xbe953e48,0x3f75bf7b,0xbf623f55,0x3ef1bf0e,
0xbef13ec4,0x3f62bf6d,0xbf753f6d,0x3e95bec4,0xbf223f0e,0x3f46bf55,0xbf7f3f7b,0x3dc9be48,0x40003f80,0x3fb53f80,0x3f80,0xbfb53f80,
0x40004000,0xbfb50000,0x0,0xbfb5c000,0x40004000,0xbfb5c000,0x0,0x3fb50000,0x40004000,0x3fb50000,0x0,0x3fb54000,
0x3fff3f80,0x3fa23f80,0xbe49bf80,0xbfc6bf80,0x3ff53ffb,0xbfe2bec8,0xbf15bec8,0xbf71bffb,0x3fe23fed,0xbf15bfed,0xbf71bf44,0x3ff53f44,
0x3fc63fd5,0x3fff3f8e,0xbfa2bf8e,0x3e493fd5,0x3ffb3f80,0x3f8e3f80,0xbec83f80,0xbfd53f80,0x3fd53fed,0xbffbbf44,0xbf8ebf44,0xbec8bfed,
0x3f8e3fb5,0x3ec8bfb5,0xbfd5bfb5,0x3ffb3fb5,0x3ec83f44,0x3fd53fed,0xbffbbfed,0xbf8e3f44,0x3ff53f80,0x3f713f80,0xbf15bf80,0xbfe2bf80,
0x3fa23fd5,0xbfffbf8e,0xbfc6bf8e,0x3e49bfd5,0x3e493f44,0x3fa2bf44,0xbfffbfed,0x3fc63fed,0xbf71bec8,0x3f153ffb,0xbfe2bffb,0xbff5bec8,
0x3fed3f80,0x3f443f80,0xbf443f80,0xbfed3f80,0x3f443fb5,0xbfedbfb5,0xbfedbfb5,0x3f44bfb5,0xbf440000,0x3fed0000,0xbfedc000,0x3f444000,
0xbfedbfb5,0xbf443fb5,0xbf44bfb5,0xbfedbfb5,0x3fe23f80,0x3f153f80,0xbf71bf80,0xbff5bf80,0x3e493f8e,0xbfc6bfd5,0xbfffbfd5,0x3fa2bf8e,
0xbfc6bf44,0x3fff3f44,0xbfa2bfed,0xbe493fed,0xbff5bffb,0xbfe23ec8,0x3f15bec8,0xbf71bffb,0x3fd53f80,0x3ec83f80,0xbf8e3f80,0xbffb3f80,
0xbec83f44,0xbf8ebfed,0xbffbbfed,0x3fd5bf44,0xbffbbfb5,0x3fd53fb5,0xbec8bfb5,0xbf8e3fb5,0xbf8ebfed,0xbffbbf44,0x3fd53f44,0x3ec8bfed,
0x3fc63f80,0x3e493f80,0xbfa2bf80,0xbfffbf80,0xbf713ec8,0xbf15bffb,0xbfe2bffb,0x3ff5bec8,0xbff5bfed,0x3f713fed,0x3f15bf44,0xbfe23f44,
0x3e49bf8e,0xbfa2bfd5,0x3fff3fd5,0x3fc6bf8e,0x3f80,0xbfb53f80,0xc0003f80,0xbfb53f80,0xc000,0x3fb50000,0x40000000,0xbfb54000,
0x4000,0x3fb5c000,0xc0000000,0x3fb50000,0xc000,0xbfb50000,0x40000000,0x3fb5c000,0xbe493f80,0xbfc63f80,0xbfffbf80,0xbfa2bf80,
0x3f15bffb,0x3f713ec8,0x3ff53ec8,0xbfe23ffb,0xbf713fed,0x3ff5bfed,0xbfe2bf44,0x3f153f44,0x3fa2bfd5,0xbe49bf8e,0x3fc63f8e,0x3fffbfd5,
0xbec83f80,0xbfd53f80,0xbffb3f80,0xbf8e3f80,0x3f8ebfed,0x3ec83f44,0x3fd53f44,0xbffb3fed,0xbfd53fb5,0x3ffbbfb5,0xbf8ebfb5,0xbec83fb5,
0x3ffbbf44,0x3f8ebfed,0x3ec83fed,0x3fd5bf44,0xbf153f80,0xbfe23f80,0xbff5bf80,0xbf71bf80,0x3fc6bfd5,0xbe493f8e,0x3fa23f8e,0xbfff3fd5,
0xbfff3f44,0x3fc6bf44,0xbe49bfed,0xbfa23fed,0x3fe23ec8,0x3ff5bffb,0xbf713ffb,0x3f153ec8,0xbf443f80,0xbfed3f80,0xbfed3f80,0xbf443f80,
0x3fedbfb5,0xbf443fb5,0x3f443fb5,0xbfed3fb5,0xbfed0000,0x3f440000,0x3f44c000,0xbfed4000,0x3f443fb5,0x3fedbfb5,0xbfed3fb5,0xbf443fb5,
0xbf713f80,0xbff53f80,0xbfe2bf80,0xbf15bf80,0x3fffbf8e,0xbfa23fd5,0x3e493fd5,0xbfc63f8e,0xbfa2bf44,0xbe493f44,0x3fc6bfed,0xbfff3fed,
0xbf153ffb,0x3f71bec8,0xbff53ec8,0xbfe23ffb,0xbf8e3f80,0xbffb3f80,0xbfd53f80,0xbec83f80,0x3ffbbf44,0xbfd53fed,0xbec83fed,0xbf8e3f44,
0xbec8bfb5,0xbf8e3fb5,0x3ffbbfb5,0xbfd53fb5,0xbfd53fed,0xbec83f44,0xbf8ebf44,0xbffb3fed,0xbfa23f80,0xbfff3f80,0xbfc6bf80,0xbe49bf80,
0x3fe2bec8,0xbff53ffb,0xbf713ffb,0xbf153ec8,0x3f15bfed,0xbfe23fed,0x3ff5bf44,0xbf713f44,0xbfff3f8e,0xbfc63fd5,0x3e49bfd5,0xbfa23f8e,
0xc0003f80,0xbfb53f80,0x3f80,0x3fb53f80,0xc0004000,0x3fb50000,0x0,0x3fb5c000,0xc0004000,0x3fb5c000,0x0,0xbfb50000,
0xc0004000,0xbfb50000,0x0,0xbfb54000,0xbfff3f80,0xbfa23f80,0x3e49bf80,0x3fc6bf80,0xbff53ffb,0x3fe2bec8,0x3f15bec8,0x3f71bffb,
0xbfe23fed,0x3f15bfed,0x3f71bf44,0xbff53f44,0xbfc63fd5,0xbfff3f8e,0x3fa2bf8e,0xbe493fd5,0xbffb3f80,0xbf8e3f80,0x3ec83f80,0x3fd53f80,
0xbfd53fed,0x3ffbbf44,0x3f8ebf44,0x3ec8bfed,0xbf8e3fb5,0xbec8bfb5,0x3fd5bfb5,0xbffb3fb5,0xbec83f44,0xbfd53fed,0x3ffbbfed,0x3f8e3f44,
0xbff53f80,0xbf713f80,0x3f15bf80,0x3fe2bf80,0xbfa23fd5,0x3fffbf8e,0x3fc6bf8e,0xbe49bfd5,0xbe493f44,0xbfa2bf44,0x3fffbfed,0xbfc63fed,
0x3f71bec8,0xbf153ffb,0x3fe2bffb,0x3ff5bec8,0xbfed3f80,0xbf443f80,0x3f443f80,0x3fed3f80,0xbf443fb5,0x3fedbfb5,0x3fedbfb5,0xbf44bfb5,
0x3f440000,0xbfed0000,0x3fedc000,0xbf444000,0x3fedbfb5,0x3f443fb5,0x3f44bfb5,0x3fedbfb5,0xbfe23f80,0xbf153f80,0x3f71bf80,0x3ff5bf80,
0xbe493f8e,0x3fc6bfd5,0x3fffbfd5,0xbfa2bf8e,0x3fc6bf44,0xbfff3f44,0x3fa2bfed,0x3e493fed,0x3ff5bffb,0x3fe23ec8,0xbf15bec8,0x3f71bffb,
0xbfd53f80,0xbec83f80,0x3f8e3f80,0x3ffb3f80,0x3ec83f44,0x3f8ebfed,0x3ffbbfed,0xbfd5bf44,0x3ffbbfb5,0xbfd53fb5,0x3ec8bfb5,0x3f8e3fb5,
0x3f8ebfed,0x3ffbbf44,0xbfd53f44,0xbec8bfed,0xbfc63f80,0xbe493f80,0x3fa2bf80,0x3fffbf80,0x3f713ec8,0x3f15bffb,0x3fe2bffb,0xbff5bec8,
0x3ff5bfed,0xbf713fed,0xbf15bf44,0x3fe23f44,0xbe49bf8e,0x3fa2bfd5,0xbfff3fd5,0xbfc6bf8e,0x3f80,0x3fb53f80,0x40003f80,0x3fb53f80,
0xc000,0xbfb50000,0xc0000000,0x3fb54000,0x4000,0xbfb5c000,0x40000000,0xbfb50000,0xc000,0x3fb50000,0xc0000000,0xbfb5c000,
0x3e493f80,0x3fc63f80,0x3fffbf80,0x3fa2bf80,0xbf15bffb,0xbf713ec8,0xbff53ec8,0x3fe23ffb,0x3f713fed,0xbff5bfed,0x3fe2bf44,0xbf153f44,
0xbfa2bfd5,0x3e49bf8e,0xbfc63f8e,0xbfffbfd5,0x3ec83f80,0x3fd53f80,0x3ffb3f80,0x3f8e3f80,0xbf8ebfed,0xbec83f44,0xbfd53f44,0x3ffb3fed,
0x3fd53fb5,0xbffbbfb5,0x3f8ebfb5,0x3ec83fb5,0xbffbbf44,0xbf8ebfed,0xbec83fed,0xbfd5bf44,0x3f153f80,0x3fe23f80,0x3ff5bf80,0x3f71bf80,
0xbfc6bfd5,0x3e493f8e,0xbfa23f8e,0x3fff3fd5,0x3fff3f44,0xbfc6bf44,0x3e49bfed,0x3fa23fed,0xbfe23ec8,0xbff5bffb,0x3f713ffb,0xbf153ec8,
0x3f443f80,0x3fed3f80,0x3fed3f80,0x3f443f80,0xbfedbfb5,0x3f443fb5,0xbf443fb5,0x3fed3fb5,0x3fed0000,0xbf440000,0xbf44c000,0x3fed4000,
0xbf443fb5,0xbfedbfb5,0x3fed3fb5,0x3f443fb5,0x3f713f80,0x3ff53f80,0x3fe2bf80,0x3f15bf80,0xbfffbf8e,0x3fa23fd5,0xbe493fd5,0x3fc63f8e,
0x3fa2bf44,0x3e493f44,0xbfc6bfed,0x3fff3fed,0x3f153ffb,0xbf71bec8,0x3ff53ec8,0x3fe23ffb,0x3f8e3f80,0x3ffb3f80,0x3fd53f80,0x3ec83f80,
0xbffbbf44,0x3fd53fed,0x3ec83fed,0x3f8e3f44,0x3ec8bfb5,0x3f8e3fb5,0xbffbbfb5,0x3fd53fb5,0x3fd53fed,0x3ec83f44,0x3f8ebf44,0x3ffb3fed,
0x3fa23f80,0x3fff3f80,0x3fc6bf80,0x3e49bf80,0xbfe2bec8,0x3ff53ffb,0x3f713ffb,0x3f153ec8,0xbf15bfed,0x3fe23fed,0xbff5bf44,0x3f713f44,
0x3fff3f8e,0x3fc63fd5,0xbe49bfd5,0x3fa23f8e,0x40004000,0x3fb54000,0x0,0xbfb50000,0x40004000,0xbfb50000,0x0,0xbfb5c000,
0x40004000,0xbfb5c000,0x0,0x3fb50000,0x40004000,0x3fb50000,0x0,0x3fb54000,0x3fa23fb5,0xbe493fb5,0xbfc6bfb5,0xbfffbfb5,
0x3f713f8e,0xbff5bfd5,0xbfe2bfd5,0x3f15bf8e,0x3f153f44,0x3f71bf44,0xbff5bfed,0x3fe23fed,0x3e493ec8,0x3fc63ffb,0xbfffbffb,0xbfa23ec8,
0xbec80000,0xbfd50000,0xbffbc000,0xbf8ec000,0xbf8ebf44,0xbec8bfed,0xbfd5bfed,0x3ffb3f44,0xbfd5bfb5,0x3ffb3fb5,0xbf8ebfb5,0xbec83fb5,
0xbffbbfed,0xbf8e3f44,0xbec8bf44,0xbfd5bfed,0xbfe2bfb5,0xbff5bfb5,0xbf71bfb5,0x3f15bfb5,0xbfffbffb,0x3fc6bec8,0x3e49bec8,0x3fa23ffb,
0xbfc6bfed,0x3e493fed,0x3fa23f44,0xbfffbf44,0xbf15bf8e,0xbfe2bfd5,0x3ff53fd5,0x3f71bf8e,0xbfedc000,0xbf44c000,0x3f440000,0x3fed0000,
0xbf44bfb5,0x3fed3fb5,0x3fed3fb5,0xbf443fb5,0x3f440000,0xbfed0000,0x3fed4000,0xbf44c000,0x3fed3fb5,0x3f44bfb5,0x3f443fb5,0x3fed3fb5,
0xbf15bfb5,0x3f71bfb5,0x3ff53fb5,0x3fe23fb5,0x3fa23ec8,0x3e493ffb,0x3fc63ffb,0xbfffbec8,0x3fff3fed,0xbfa2bfed,0xbe493f44,0x3fc6bf44,
0x3f713fd5,0x3ff53f8e,0xbfe2bf8e,0xbf153fd5,0x3f8e0000,0x3ffb0000,0x3fd54000,0x3ec84000,0x3ffb3fed,0xbfd53f44,0xbec83f44,0xbf8ebfed,
0x3ec83fb5,0x3f8ebfb5,0xbffbbfb5,0x3fd53fb5,0xbfd5bf44,0xbec83fed,0xbf8ebfed,0xbffbbf44,0x3fff3fb5,0x3fc63fb5,0x3e493fb5,0xbfa23fb5,
0x3f153fd5,0xbfe2bf8e,0xbff5bf8e,0x3f71bfd5,0xbfe2bf44,0x3ff53f44,0xbf71bfed,0xbf153fed,0xbfa2bffb,0xbfffbec8,0x3fc63ec8,0x3e49bffb,
0x4000,0xbfb54000,0xc0000000,0xbfb50000,0xc000,0x3fb50000,0x40000000,0xbfb54000,0x4000,0x3fb5c000,0xc0000000,0x3fb50000,
0xc000,0xbfb50000,0x40000000,0x3fb5c000,0xbfc63fb5,0xbfff3fb5,0xbfa2bfb5,0x3e49bfb5,0x3fe2bf8e,0xbf153fd5,0x3f713fd5,0xbff53f8e,
0xbff53f44,0x3fe2bf44,0xbf15bfed,0xbf713fed,0x3fffbec8,0x3fa2bffb,0x3e493ffb,0x3fc6bec8,0xbffb0000,0xbf8e0000,0x3ec8c000,0x3fd5c000,
0x3fd53f44,0xbffb3fed,0xbf8e3fed,0xbec8bf44,0xbf8ebfb5,0xbec83fb5,0x3fd5bfb5,0xbffb3fb5,0x3ec83fed,0x3fd5bf44,0xbffb3f44,0xbf8e3fed,
0xbf71bfb5,0x3f15bfb5,0x3fe2bfb5,0x3ff5bfb5,0xbe493ffb,0xbfa23ec8,0xbfff3ec8,0x3fc6bffb,0x3fa2bfed,0xbfff3fed,0x3fc63f44,0xbe49bf44,
0xbff53f8e,0xbf713fd5,0xbf15bfd5,0xbfe23f8e,0x3f44c000,0x3fedc000,0x3fed0000,0x3f440000,0xbfed3fb5,0x3f44bfb5,0xbf44bfb5,0x3fedbfb5,
0x3fed0000,0xbf440000,0xbf444000,0x3fedc000,0xbf44bfb5,0xbfed3fb5,0x3fedbfb5,0x3f44bfb5,0x3ff5bfb5,0x3fe2bfb5,0x3f153fb5,0xbf713fb5,
0xbfc6bec8,0x3fffbffb,0x3fa2bffb,0x3e493ec8,0xbe493fed,0x3fc6bfed,0xbfff3f44,0x3fa2bf44,0x3fe2bfd5,0x3f15bf8e,0x3f713f8e,0x3ff5bfd5,
0x3fd50000,0x3ec80000,0xbf8e4000,0xbffb4000,0x3ec8bfed,0x3f8ebf44,0x3ffbbf44,0xbfd53fed,0xbffb3fb5,0x3fd5bfb5,0xbec8bfb5,0xbf8e3fb5,
0x3f8e3f44,0x3ffbbfed,0xbfd53fed,0xbec83f44,0x3e493fb5,0xbfa23fb5,0xbfff3fb5,0xbfc63fb5,0x3ff5bfd5,0xbf713f8e,0x3f153f8e,0xbfe23fd5,
0xbf71bf44,0xbf153f44,0x3fe2bfed,0xbff53fed,0xbfc63ffb,0xbe493ec8,0xbfa2bec8,0xbfff3ffb,0xc0004000,0xbfb54000,0x0,0x3fb50000,
0xc0004000,0x3fb50000,0x0,0x3fb5c000,0xc0004000,0x3fb5c000,0x0,0xbfb50000,0xc0004000,0xbfb50000,0x0,0xbfb54000,
0xbfa23fb5,0x3e493fb5,0x3fc6bfb5,0x3fffbfb5,0xbf713f8e,0x3ff5bfd5,0x3fe2bfd5,0xbf15bf8e,0xbf153f44,0xbf71bf44,0x3ff5bfed,0xbfe23fed,
0xbe493ec8,0xbfc63ffb,0x3fffbffb,0x3fa23ec8,0x3ec80000,0x3fd50000,0x3ffbc000,0x3f8ec000,0x3f8ebf44,0x3ec8bfed,0x3fd5bfed,0xbffb3f44,
0x3fd5bfb5,0xbffb3fb5,0x3f8ebfb5,0x3ec83fb5,0x3ffbbfed,0x3f8e3f44,0x3ec8bf44,0x3fd5bfed,0x3fe2bfb5,0x3ff5bfb5,0x3f71bfb5,0xbf15bfb5,
0x3fffbffb,0xbfc6bec8,0xbe49bec8,0xbfa23ffb,0x3fc6bfed,0xbe493fed,0xbfa23f44,0x3fffbf44,0x3f15bf8e,0x3fe2bfd5,0xbff53fd5,0xbf71bf8e,
0x3fedc000,0x3f44c000,0xbf440000,0xbfed0000,0x3f44bfb5,0xbfed3fb5,0xbfed3fb5,0x3f443fb5,0xbf440000,0x3fed0000,0xbfed4000,0x3f44c000,
0xbfed3fb5,0xbf44bfb5,0xbf443fb5,0xbfed3fb5,0x3f15bfb5,0xbf71bfb5,0xbff53fb5,0xbfe23fb5,0xbfa23ec8,0xbe493ffb,0xbfc63ffb,0x3fffbec8,
0xbfff3fed,0x3fa2bfed,0x3e493f44,0xbfc6bf44,0xbf713fd5,0xbff53f8e,0x3fe2bf8e,0x3f153fd5,0xbf8e0000,0xbffb0000,0xbfd54000,0xbec84000,
0xbffb3fed,0x3fd53f44,0x3ec83f44,0x3f8ebfed,0xbec83fb5,0xbf8ebfb5,0x3ffbbfb5,0xbfd53fb5,0x3fd5bf44,0x3ec83fed,0x3f8ebfed,0x3ffbbf44,
0xbfff3fb5,0xbfc63fb5,0xbe493fb5,0x3fa23fb5,0xbf153fd5,0x3fe2bf8e,0x3ff5bf8e,0xbf71bfd5,0x3fe2bf44,0xbff53f44,0x3f71bfed,0x3f153fed,
0x3fa2bffb,0x3fffbec8,0xbfc63ec8,0xbe49bffb,0x4000,0x3fb54000,0x40000000,0x3fb50000,0xc000,0xbfb50000,0xc0000000,0x3fb54000,
0x4000,0xbfb5c000,0x40000000,0xbfb50000,0xc000,0x3fb50000,0xc0000000,0xbfb5c000,0x3fc63fb5,0x3fff3fb5,0x3fa2bfb5,0xbe49bfb5,
0xbfe2bf8e,0x3f153fd5,0xbf713fd5,0x3ff53f8e,0x3ff53f44,0xbfe2bf44,0x3f15bfed,0x3f713fed,0xbfffbec8,0xbfa2bffb,0xbe493ffb,0xbfc6bec8,
0x3ffb0000,0x3f8e0000,0xbec8c000,0xbfd5c000,0xbfd53f44,0x3ffb3fed,0x3f8e3fed,0x3ec8bf44,0x3f8ebfb5,0x3ec83fb5,0xbfd5bfb5,0x3ffb3fb5,
0xbec83fed,0xbfd5bf44,0x3ffb3f44,0x3f8e3fed,0x3f71bfb5,0xbf15bfb5,0xbfe2bfb5,0xbff5bfb5,0x3e493ffb,0x3fa23ec8,0x3fff3ec8,0xbfc6bffb,
0xbfa2bfed,0x3fff3fed,0xbfc63f44,0x3e49bf44,0x3ff53f8e,0x3f713fd5,0x3f15bfd5,0x3fe23f8e,0xbf44c000,0xbfedc000,0xbfed0000,0xbf440000,
0x3fed3fb5,0xbf44bfb5,0x3f44bfb5,0xbfedbfb5,0xbfed0000,0x3f440000,0x3f444000,0xbfedc000,0x3f44bfb5,0x3fed3fb5,0xbfedbfb5,0xbf44bfb5,
0xbff5bfb5,0xbfe2bfb5,0xbf153fb5,0x3f713fb5,0x3fc6bec8,0xbfffbffb,0xbfa2bffb,0xbe493ec8,0x3e493fed,0xbfc6bfed,0x3fff3f44,0xbfa2bf44,
0xbfe2bfd5,0xbf15bf8e,0xbf713f8e,0xbff5bfd5,0xbfd50000,0xbec80000,0x3f8e4000,0x3ffb4000,0xbec8bfed,0xbf8ebf44,0xbffbbf44,0x3fd53fed,
0x3ffb3fb5,0xbfd5bfb5,0x3ec8bfb5,0x3f8e3fb5,0xbf8e3f44,0xbffbbfed,0x3fd53fed,0x3ec83f44,0xbe493fb5,0x3fa23fb5,0x3fff3fb5,0x3fc63fb5,
0xbff5bfd5,0x3f713f8e,0xbf153f8e,0x3fe23fd5,0x3f71bf44,0x3f153f44,0xbfe2bfed,0x3ff53fed,0x3fc63ffb,0x3e493ec8,0x3fa2bec8,0x3fff3ffb,
0x40004000,0x3fb54000,0x0,0xbfb50000,0x40004000,0xbfb50000,0x0,0xbfb5c000,0x40004000,0xbfb5c000,0x0,0x3fb50000,
0x40004000,0x3fb50000,0x0,0x3fb54000,0xbe490000,0xbfc60000,0xbfffc000,0xbfa2c000,0xbf15bec8,0xbf71bffb,0xbff5bffb,0x3fe23ec8,
0xbf71bf44,0x3ff53f44,0xbfe2bfed,0x3f153fed,0xbfa2bf8e,0x3e493fd5,0xbfc6bfd5,0xbfffbf8e,0xbffbc000,0xbf8ec000,0x3ec80000,0x3fd50000,
0xbfd5bfed,0x3ffb3f44,0x3f8e3f44,0x3ec83fed,0xbf8ebfb5,0xbec83fb5,0x3fd53fb5,0xbffbbfb5,0xbec8bf44,0xbfd5bfed,0x3ffb3fed,0x3f8ebf44,
0x3f150000,0x3fe20000,0x3ff54000,0x3f714000,0x3fc63f8e,0xbe493fd5,0x3fa23fd5,0xbfffbf8e,0x3fff3fed,0xbfc6bfed,0x3e493f44,0x3fa2bf44,
0x3fe23ffb,0x3ff53ec8,0xbf71bec8,0x3f153ffb,0x3fed4000,0x3f444000,0xbf440000,0xbfed0000,0x3f443fb5,0xbfedbfb5,0xbfedbfb5,0x3f44bfb5,
0xbf440000,0x3fed0000,0xbfedc000,0x3f444000,0xbfedbfb5,0xbf443fb5,0xbf44bfb5,0xbfedbfb5,0xbf710000,0xbff50000,0xbfe2c000,0xbf15c000,
0xbfffbfd5,0x3fa2bf8e,0xbe49bf8e,0x3fc63fd5,0xbfa2bfed,0xbe493fed,0x3fc63f44,0xbfffbf44,0x3f15bec8,0xbf71bffb,0x3ff53ffb,0x3fe2bec8,
0xbfd5c000,0xbec8c000,0x3f8e0000,0x3ffb0000,0x3ec8bf44,0x3f8e3fed,0x3ffb3fed,0xbfd53f44,0x3ffb3fb5,0xbfd5bfb5,0x3ec83fb5,0x3f8ebfb5,
0x3f8e3fed,0x3ffb3f44,0xbfd5bf44,0xbec83fed,0x3fa20000,0x3fff0000,0x3fc64000,0x3e494000,0x3fe23ffb,0xbff53ec8,0xbf713ec8,0xbf15bffb,
0xbf153f44,0x3fe2bf44,0xbff5bfed,0x3f713fed,0xbfffbfd5,0xbfc63f8e,0x3e49bf8e,0xbfa2bfd5,0x4000,0xbfb54000,0xc0000000,0xbfb50000,
0xc000,0x3fb50000,0x40000000,0xbfb54000,0x4000,0x3fb5c000,0xc0000000,0x3fb50000,0xc000,0xbfb50000,0x40000000,0x3fb5c000,
0xbfff0000,0xbfa20000,0x3e49c000,0x3fc6c000,0x3ff53ec8,0xbfe23ffb,0xbf153ffb,0xbf71bec8,0xbfe2bf44,0x3f153f44,0x3f71bfed,0xbff53fed,
0x3fc63f8e,0x3fffbfd5,0xbfa23fd5,0x3e493f8e,0x3ec8c000,0x3fd5c000,0x3ffb0000,0x3f8e0000,0xbf8e3fed,0xbec8bf44,0xbfd5bf44,0x3ffbbfed,
0x3fd5bfb5,0xbffb3fb5,0x3f8e3fb5,0x3ec8bfb5,0xbffb3f44,0xbf8e3fed,0xbec8bfed,0xbfd53f44,0x3ff50000,0x3f710000,0xbf154000,0xbfe24000,
0xbfa2bf8e,0x3fffbfd5,0x3fc6bfd5,0xbe493f8e,0x3e493fed,0x3fa2bfed,0xbfff3f44,0x3fc6bf44,0x3f71bffb,0xbf15bec8,0x3fe23ec8,0x3ff5bffb,
0xbf444000,0xbfed4000,0xbfed0000,0xbf440000,0x3fedbfb5,0xbf443fb5,0x3f443fb5,0xbfed3fb5,0xbfed0000,0x3f440000,0x3f44c000,0xbfed4000,
0x3f443fb5,0x3fedbfb5,0xbfed3fb5,0xbf443fb5,0xbfe20000,0xbf150000,0x3f71c000,0x3ff5c000,0x3e493fd5,0xbfc63f8e,0xbfff3f8e,0x3fa2bfd5,
0x3fc6bfed,0xbfff3fed,0x3fa23f44,0x3e49bf44,0xbff53ec8,0xbfe23ffb,0x3f15bffb,0xbf713ec8,0x3f8ec000,0x3ffbc000,0x3fd50000,0x3ec80000,
0xbffb3f44,0x3fd5bfed,0x3ec8bfed,0x3f8ebf44,0x3ec83fb5,0x3f8ebfb5,0xbffb3fb5,0x3fd5bfb5,0x3fd5bfed,0x3ec8bf44,0x3f8e3f44,0x3ffbbfed,
0x3fc60000,0x3e490000,0xbfa24000,0xbfff4000,0x3f71bffb,0x3f15bec8,0x3fe2bec8,0xbff53ffb,0xbff53f44,0x3f71bf44,0x3f15bfed,0xbfe23fed,
0xbe493fd5,0x3fa2bf8e,0xbfff3f8e,0xbfc63fd5,0xc0004000,0xbfb54000,0x0,0x3fb50000,0xc0004000,0x3fb50000,0x0,0x3fb5c000,
0xc0004000,0x3fb5c000,0x0,0xbfb50000,0xc0004000,0xbfb50000,0x0,0xbfb54000,0x3e490000,0x3fc60000,0x3fffc000,0x3fa2c000,
0x3f15bec8,0x3f71bffb,0x3ff5bffb,0xbfe23ec8,0x3f71bf44,0xbff53f44,0x3fe2bfed,0xbf153fed,0x3fa2bf8e,0xbe493fd5,0x3fc6bfd5,0x3fffbf8e,
0x3ffbc000,0x3f8ec000,0xbec80000,0xbfd50000,0x3fd5bfed,0xbffb3f44,0xbf8e3f44,0xbec83fed,0x3f8ebfb5,0x3ec83fb5,0xbfd53fb5,0x3ffbbfb5,
0x3ec8bf44,0x3fd5bfed,0xbffb3fed,0xbf8ebf44,0xbf150000,0xbfe20000,0xbff54000,0xbf714000,0xbfc63f8e,0x3e493fd5,0xbfa23fd5,0x3fffbf8e,
0xbfff3fed,0x3fc6bfed,0xbe493f44,0xbfa2bf44,0xbfe23ffb,0xbff53ec8,0x3f71bec8,0xbf153ffb,0xbfed4000,0xbf444000,0x3f440000,0x3fed0000,
0xbf443fb5,0x3fedbfb5,0x3fedbfb5,0xbf44bfb5,0x3f440000,0xbfed0000,0x3fedc000,0xbf444000,0x3fedbfb5,0x3f443fb5,0x3f44bfb5,0x3fedbfb5,
0x3f710000,0x3ff50000,0x3fe2c000,0x3f15c000,0x3fffbfd5,0xbfa2bf8e,0x3e49bf8e,0xbfc63fd5,0x3fa2bfed,0x3e493fed,0xbfc63f44,0x3fffbf44,
0xbf15bec8,0x3f71bffb,0xbff53ffb,0xbfe2bec8,0x3fd5c000,0x3ec8c000,0xbf8e0000,0xbffb0000,0xbec8bf44,0xbf8e3fed,0xbffb3fed,0x3fd53f44,
0xbffb3fb5,0x3fd5bfb5,0xbec83fb5,0xbf8ebfb5,0xbf8e3fed,0xbffb3f44,0x3fd5bf44,0x3ec83fed,0xbfa20000,0xbfff0000,0xbfc64000,0xbe494000,
0xbfe23ffb,0x3ff53ec8,0x3f713ec8,0x3f15bffb,0x3f153f44,0xbfe2bf44,0x3ff5bfed,0xbf713fed,0x3fffbfd5,0x3fc63f8e,0xbe49bf8e,0x3fa2bfd5,
0x4000,0x3fb54000,0x40000000,0x3fb50000,0xc000,0xbfb50000,0xc0000000,0x3fb54000,0x4000,0xbfb5c000,0x40000000,0xbfb50000,
0xc000,0x3fb50000,0xc0000000,0xbfb5c000,0x3fff0000,0x3fa20000,0xbe49c000,0xbfc6c000,0xbff53ec8,0x3fe23ffb,0x3f153ffb,0x3f71bec8,
0x3fe2bf44,0xbf153f44,0xbf71bfed,0x3ff53fed,0xbfc63f8e,0xbfffbfd5,0x3fa23fd5,0xbe493f8e,0xbec8c000,0xbfd5c000,0xbffb0000,0xbf8e0000,
0x3f8e3fed,0x3ec8bf44,0x3fd5bf44,0xbffbbfed,0xbfd5bfb5,0x3ffb3fb5,0xbf8e3fb5,0xbec8bfb5,0x3ffb3f44,0x3f8e3fed,0x3ec8bfed,0x3fd53f44,
0xbff50000,0xbf710000,0x3f154000,0x3fe24000,0x3fa2bf8e,0xbfffbfd5,0xbfc6bfd5,0x3e493f8e,0xbe493fed,0xbfa2bfed,0x3fff3f44,0xbfc6bf44,
0xbf71bffb,0x3f15bec8,0xbfe23ec8,0xbff5bffb,0x3f444000,0x3fed4000,0x3fed0000,0x3f440000,0xbfedbfb5,0x3f443fb5,0xbf443fb5,0x3fed3fb5,
0x3fed0000,0xbf440000,0xbf44c000,0x3fed4000,0xbf443fb5,0xbfedbfb5,0x3fed3fb5,0x3f443fb5,0x3fe20000,0x3f150000,0xbf71c000,0xbff5c000,
0xbe493fd5,0x3fc63f8e,0x3fff3f8e,0xbfa2bfd5,0xbfc6bfed,0x3fff3fed,0xbfa23f44,0xbe49bf44,0x3ff53ec8,0x3fe23ffb,0xbf15bffb,0x3f713ec8,
0xbf8ec000,0xbffbc000,0xbfd50000,0xbec80000,0x3ffb3f44,0xbfd5bfed,0xbec8bfed,0xbf8ebf44,0xbec83fb5,0xbf8ebfb5,0x3ffb3fb5,0xbfd5bfb5,
0xbfd5bfed,0xbec8bf44,0xbf8e3f44,0xbffbbfed,0xbfc60000,0xbe490000,0x3fa24000,0x3fff4000,0xbf71bffb,0xbf15bec8,0xbfe2bec8,0x3ff53ffb,
0x3ff53f44,0xbf71bf44,0xbf15bfed,0x3fe23fed,0x3e493fd5,0xbfa2bf8e,0x3fff3f8e,0x3fc63fd5,0x40004000,0x3fb54000,0x0,0xbfb50000,
0x40004000,0xbfb50000,0x0,0xbfb5c000,0x40004000,0xbfb5c000,0x0,0x3fb50000,0x40004000,0x3fb50000,0x0,0x3fb54000,
0xbfc6bfb5,0xbfffbfb5,0xbfa2bfb5,0x3e49bfb5,0xbfe2bfd5,0x3f15bf8e,0xbf71bf8e,0x3ff53fd5,0xbff5bfed,0x3fe23fed,0xbf15bf44,0xbf713f44,
0xbfffbffb,0xbfa23ec8,0xbe49bec8,0xbfc6bffb,0x3ec80000,0x3fd50000,0x3ffb4000,0x3f8e4000,0x3f8e3f44,0x3ec83fed,0x3fd53fed,0xbffbbf44,
0x3fd53fb5,0xbffbbfb5,0x3f8e3fb5,0x3ec8bfb5,0x3ffb3fed,0x3f8ebf44,0x3ec83f44,0x3fd53fed,0x3f713fb5,0xbf153fb5,0xbfe2bfb5,0xbff5bfb5,
0xbe493ec8,0xbfa2bffb,0xbfffbffb,0x3fc6bec8,0xbfa2bf44,0x3fff3f44,0xbfc6bfed,0x3e493fed,0xbff5bfd5,0xbf713f8e,0xbf15bf8e,0xbfe2bfd5,
0xbfedc000,0xbf44c000,0x3f440000,0x3fed0000,0xbf44bfb5,0x3fed3fb5,0x3fed3fb5,0xbf443fb5,0x3f440000,0xbfed0000,0x3fed4000,0xbf44c000,
0x3fed3fb5,0x3f44bfb5,0x3f443fb5,0x3fed3fb5,0x3ff53fb5,0x3fe23fb5,0x3f153fb5,0xbf713fb5,0x3fc63ffb,0xbfffbec8,0xbfa2bec8,0xbe49bffb,
0xbe493f44,0x3fc6bf44,0xbfffbfed,0x3fa23fed,0xbfe2bf8e,0xbf153fd5,0xbf71bfd5,0xbff5bf8e,0xbf8e0000,0xbffb0000,0xbfd5c000,0xbec8c000,
0xbffbbfed,0x3fd5bf44,0x3ec8bf44,0x3f8e3fed,0xbec8bfb5,0xbf8e3fb5,0x3ffb3fb5,0xbfd5bfb5,0x3fd53f44,0x3ec8bfed,0x3f8e3fed,0x3ffb3f44,
0xbe49bfb5,0x3fa2bfb5,0x3fff3fb5,0x3fc63fb5,0x3ff53f8e,0xbf713fd5,0x3f153fd5,0xbfe2bf8e,0x3f713fed,0x3f15bfed,0xbfe2bf44,0x3ff53f44,
0xbfc6bec8,0xbe493ffb,0xbfa2bffb,0xbfffbec8,0x4000,0xbfb54000,0xc0000000,0xbfb50000,0xc000,0x3fb50000,0x40000000,0xbfb54000,
0x4000,0x3fb5c000,0xc0000000,0x3fb50000,0xc000,0xbfb50000,0x40000000,0x3fb5c000,0xbfa2bfb5,0x3e49bfb5,0x3fc6bfb5,0x3fffbfb5,
0x3f713fd5,0xbff53f8e,0xbfe23f8e,0x3f15bfd5,0xbf15bfed,0xbf713fed,0x3ff5bf44,0xbfe23f44,0x3e493ffb,0x3fc6bec8,0xbfff3ec8,0xbfa23ffb,
0x3ffb0000,0x3f8e0000,0xbec84000,0xbfd54000,0xbfd5bf44,0x3ffbbfed,0x3f8ebfed,0x3ec83f44,0x3f8e3fb5,0x3ec8bfb5,0xbfd53fb5,0x3ffbbfb5,
0xbec8bfed,0xbfd53f44,0x3ffbbf44,0x3f8ebfed,0xbfe23fb5,0xbff53fb5,0xbf71bfb5,0x3f15bfb5,0x3fffbec8,0xbfc63ffb,0xbe493ffb,0xbfa23ec8,
0xbfc6bf44,0x3e493f44,0x3fa2bfed,0xbfff3fed,0x3f153fd5,0x3fe2bf8e,0xbff53f8e,0xbf713fd5,0x3f44c000,0x3fedc000,0x3fed0000,0x3f440000,
0xbfed3fb5,0x3f44bfb5,0xbf44bfb5,0x3fedbfb5,0x3fed0000,0xbf440000,0xbf444000,0x3fedc000,0xbf44bfb5,0xbfed3fb5,0x3fedbfb5,0x3f44bfb5,
0x3f153fb5,0xbf713fb5,0xbff53fb5,0xbfe23fb5,0x3fa2bffb,0x3e493ec8,0x3fc63ec8,0xbfff3ffb,0xbfff3f44,0x3fa2bf44,0x3e49bfed,0xbfc63fed,
0x3f713f8e,0x3ff5bfd5,0xbfe23fd5,0xbf153f8e,0xbfd50000,0xbec80000,0x3f8ec000,0x3ffbc000,0xbec83fed,0xbf8e3f44,0xbffb3f44,0x3fd5bfed,
0x3ffbbfb5,0xbfd53fb5,0x3ec83fb5,0x3f8ebfb5,0xbf8ebf44,0xbffb3fed,0x3fd5bfed,0x3ec8bf44,0x3fffbfb5,0x3fc6bfb5,0x3e493fb5,0xbfa23fb5,
0xbf15bf8e,0x3fe2bfd5,0x3ff5bfd5,0xbf713f8e,0xbfe23fed,0x3ff5bfed,0xbf71bf44,0xbf153f44,0x3fa23ec8,0x3fffbffb,0xbfc63ffb,0xbe493ec8,
0xc0004000,0xbfb54000,0x0,0x3fb50000,0xc0004000,0x3fb50000,0x0,0x3fb5c000,0xc0004000,0x3fb5c000,0x0,0xbfb50000,
0xc0004000,0xbfb50000,0x0,0xbfb54000,0x3fc6bfb5,0x3fffbfb5,0x3fa2bfb5,0xbe49bfb5,0x3fe2bfd5,0xbf15bf8e,0x3f71bf8e,0xbff53fd5,
0x3ff5bfed,0xbfe23fed,0x3f15bf44,0x3f713f44,0x3fffbffb,0x3fa23ec8,0x3e49bec8,0x3fc6bffb,0xbec80000,0xbfd50000,0xbffb4000,0xbf8e4000,
0xbf8e3f44,0xbec83fed,0xbfd53fed,0x3ffbbf44,0xbfd53fb5,0x3ffbbfb5,0xbf8e3fb5,0xbec8bfb5,0xbffb3fed,0xbf8ebf44,0xbec83f44,0xbfd53fed,
0xbf713fb5,0x3f153fb5,0x3fe2bfb5,0x3ff5bfb5,0x3e493ec8,0x3fa2bffb,0x3fffbffb,0xbfc6bec8,0x3fa2bf44,0xbfff3f44,0x3fc6bfed,0xbe493fed,
0x3ff5bfd5,0x3f713f8e,0x3f15bf8e,0x3fe2bfd5,0x3fedc000,0x3f44c000,0xbf440000,0xbfed0000,0x3f44bfb5,0xbfed3fb5,0xbfed3fb5,0x3f443fb5,
0xbf440000,0x3fed0000,0xbfed4000,0x3f44c000,0xbfed3fb5,0xbf44bfb5,0xbf443fb5,0xbfed3fb5,0xbff53fb5,0xbfe23fb5,0xbf153fb5,0x3f713fb5,
0xbfc63ffb,0x3fffbec8,0x3fa2bec8,0x3e49bffb,0x3e493f44,0xbfc6bf44,0x3fffbfed,0xbfa23fed,0x3fe2bf8e,0x3f153fd5,0x3f71bfd5,0x3ff5bf8e,
0x3f8e0000,0x3ffb0000,0x3fd5c000,0x3ec8c000,0x3ffbbfed,0xbfd5bf44,0xbec8bf44,0xbf8e3fed,0x3ec8bfb5,0x3f8e3fb5,0xbffb3fb5,0x3fd5bfb5,
0xbfd53f44,0xbec8bfed,0xbf8e3fed,0xbffb3f44,0x3e49bfb5,0xbfa2bfb5,0xbfff3fb5,0xbfc63fb5,0xbff53f8e,0x3f713fd5,0xbf153fd5,0x3fe2bf8e,
0xbf713fed,0xbf15bfed,0x3fe2bf44,0xbff53f44,0x3fc6bec8,0x3e493ffb,0x3fa2bffb,0x3fffbec8,0x4000,0x3fb54000,0x40000000,0x3fb50000,
0xc000,0xbfb50000,0xc0000000,0x3fb54000,0x4000,0xbfb5c000,0x40000000,0xbfb50000,0xc000,0x3fb50000,0xc0000000,0xbfb5c000,
0x3fa2bfb5,0xbe49bfb5,0xbfc6bfb5,0xbfffbfb5,0xbf713fd5,0x3ff53f8e,0x3fe23f8e,0xbf15bfd5,0x3f15bfed,0x3f713fed,0xbff5bf44,0x3fe23f44,
0xbe493ffb,0xbfc6bec8,0x3fff3ec8,0x3fa23ffb,0xbffb0000,0xbf8e0000,0x3ec84000,0x3fd54000,0x3fd5bf44,0xbffbbfed,0xbf8ebfed,0xbec83f44,
0xbf8e3fb5,0xbec8bfb5,0x3fd53fb5,0xbffbbfb5,0x3ec8bfed,0x3fd53f44,0xbffbbf44,0xbf8ebfed,0x3fe23fb5,0x3ff53fb5,0x3f71bfb5,0xbf15bfb5,
0xbfffbec8,0x3fc63ffb,0x3e493ffb,0x3fa23ec8,0x3fc6bf44,0xbe493f44,0xbfa2bfed,0x3fff3fed,0xbf153fd5,0xbfe2bf8e,0x3ff53f8e,0x3f713fd5,
0xbf44c000,0xbfedc000,0xbfed0000,0xbf440000,0x3fed3fb5,0xbf44bfb5,0x3f44bfb5,0xbfedbfb5,0xbfed0000,0x3f440000,0x3f444000,0xbfedc000,
0x3f44bfb5,0x3fed3fb5,0xbfedbfb5,0xbf44bfb5,0xbf153fb5,0x3f713fb5,0x3ff53fb5,0x3fe23fb5,0xbfa2bffb,0xbe493ec8,0xbfc63ec8,0x3fff3ffb,
0x3fff3f44,0xbfa2bf44,0xbe49bfed,0x3fc63fed,0xbf713f8e,0xbff5bfd5,0x3fe23fd5,0x3f153f8e,0x3fd50000,0x3ec80000,0xbf8ec000,0xbffbc000,
0x3ec83fed,0x3f8e3f44,0x3ffb3f44,0xbfd5bfed,0xbffbbfb5,0x3fd53fb5,0xbec83fb5,0xbf8ebfb5,0x3f8ebf44,0x3ffb3fed,0xbfd5bfed,0xbec8bf44,
0xbfffbfb5,0xbfc6bfb5,0xbe493fb5,0x3fa23fb5,0x3f15bf8e,0xbfe2bfd5,0xbff5bfd5,0x3f713f8e,0x3fe23fed,0xbff5bfed,0x3f71bf44,0x3f153f44,
0xbfa23ec8,0xbfffbffb,0x3fc63ffb,0x3e493ec8,0x80003f80,0x3f800000,0x80003f80,0x3f800000,0x80003f80,0x3f800000,0x80003f80,0x3f800000,
0x80003f80,0x3f800000,0x80003f80,0x3f800000,0x80003f80,0x3f800000,0x80003f80,0x3f800000,0x80003f80,0x3f800000,0x8000bf80,0xbf800000,
0x3f353f35,0x3f35bf35,0xbf35bf35,0xbf353f35,0x3f800000,0xbf80,0xbf800000,0x3f80,0x3f35bf35,0xbf35bf35,0xbf353f35,0x3f353f35,
0x80003f80,0x3f800000,0x80003f80,0x3f800000,0x3f800000,0xbf80,0x3f800000,0xbf80,0x8000bf80,0xbf800000,0x8000bf80,0xbf800000,
0xbf800000,0x3f80,0xbf800000,0x3f80,0x80003f80,0x3f800000,0x8000bf80,0xbf800000,0x3f35bf35,0xbf35bf35,0xbf353f35,0x3f353f35,
0xbf800000,0x3f80,0x3f800000,0xbf80,0x3f353f35,0x3f35bf35,0xbf35bf35,0xbf353f35,0x80003f80,0x3f800000,0x80003f80,0x3f800000,
0x8000bf80,0xbf800000,0x8000bf80,0xbf800000,0x80003f80,0x3f800000,0x80003f80,0x3f800000,0x8000bf80,0xbf800000,0x8000bf80,0xbf800000,
0x80003f80,0x3f800000,0x8000bf80,0xbf800000,0xbf35bf35,0xbf353f35,0x3f353f35,0x3f35bf35,0x3f800000,0xbf80,0xbf800000,0x3f80,
0xbf353f35,0x3f353f35,0x3f35bf35,0xbf35bf35,0x80003f80,0x3f800000,0x80003f80,0x3f800000,0xbf800000,0x3f80,0xbf800000,0x3f80,
0x8000bf80,0xbf800000,0x8000bf80,0xbf800000,0x3f800000,0xbf80,0x3f800000,0xbf80,0x80003f80,0x3f800000,0x8000bf80,0xbf800000,
0xbf353f35,0x3f353f35,0x3f35bf35,0xbf35bf35,0xbf800000,0x3f80,0x3f800000,0xbf80,0xbf35bf35,0xbf353f35,0x3f353f35,0x3f35bf35,
0x3f803f80,0x80008000,0x80008000,0xbf80bf80,0x3f803f80,0x80008000,0x80008000,0xbf80bf80,0x3f803f80,0x80008000,0x80008000,0xbf80bf80,
0x3f803f80,0x80008000,0x80008000,0xbf80bf80,0x3f353f80,0x3f358000,0x3f358000,0xbf35bf80,0xbf350000,0x3f353f80,0x3f353f80,0x3f358000,
0xbf35bf80,0xbf358000,0xbf358000,0x3f353f80,0x3f350000,0xbf35bf80,0xbf35bf80,0xbf358000,0x3f80,0x3f808000,0x3f808000,0x8000bf80,
0xbf80,0xbf808000,0xbf808000,0x80003f80,0x3f80,0x3f808000,0x3f808000,0x8000bf80,0xbf80,0xbf808000,0xbf808000,0x80003f80,
0xbf353f80,0x3f358000,0x3f358000,0x3f35bf80,0x3f350000,0x3f35bf80,0x3f35bf80,0xbf358000,0x3f35bf80,0xbf358000,0xbf358000,0xbf353f80,
0xbf350000,0xbf353f80,0xbf353f80,0x3f358000,0xbf803f80,0x80008000,0x80008000,0x3f80bf80,0xbf803f80,0x80008000,0x80008000,0x3f80bf80,
0xbf803f80,0x80008000,0x80008000,0x3f80bf80,0xbf803f80,0x80008000,0x80008000,0x3f80bf80,0xbf353f80,0xbf358000,0xbf358000,0x3f35bf80,
0x3f350000,0xbf353f80,0xbf353f80,0xbf358000,0x3f35bf80,0x3f358000,0x3f358000,0xbf353f80,0xbf350000,0x3f35bf80,0x3f35bf80,0x3f358000,
0x3f80,0xbf808000,0xbf808000,0x8000bf80,0xbf80,0x3f808000,0x3f808000,0x80003f80,0x3f80,0xbf808000,0xbf808000,0x8000bf80,
0xbf80,0x3f808000,0x3f808000,0x80003f80,0x3f353f80,0xbf358000,0xbf358000,0xbf35bf80,0xbf350000,0xbf35bf80,0xbf35bf80,0x3f358000,
0xbf35bf80,0x3f358000,0x3f358000,0x3f353f80,0x3f350000,0x3f353f80,0x3f353f80,0xbf358000,0x3f800000,0x0,0x3f800000,0x0,
0x3f800000,0x0,0x3f800000,0x0,0x3f800000,0x0,0x3f800000,0x0,0x3f800000,0x0,0x3f800000,0x0,
0x3f800000,0x0,0x3f7fb10f,0xbd48fb30,0x3f7ec46d,0xbdc8bd36,0x3f7d3aac,0xbe164083,0x3f7b14be,0xbe47c5c2,0x3f7853f8,0xbe78cfcc,
0x3f74fa0b,0xbe94a031,0x3f710908,0xbeac7cd4,0x3f800000,0x0,0x3f7ec46d,0xbdc8bd36,0x3f7b14be,0xbe47c5c2,0x3f74fa0b,0xbe94a031,
0x3f6c835e,0xbec3ef15,0x3f61c598,0xbef15aea,0x3f54db31,0xbf0e39da,0x3f45e403,0xbf226799,0x3f800000,0x0,0x3f7d3aac,0xbe164083,
0x3f74fa0b,0xbe94a031,0x3f676bd8,0xbedae880,0x3f54db31,0xbf0e39da,0x3f3daef9,0xbf2beb4a,0x3f226799,0xbf45e403,0x3f039c3d,0xbf5b941a,
0x3f800000,0x0,0x3f7b14be,0xbe47c5c2,0x3f6c835e,0xbec3ef15,0x3f54db31,0xbf0e39da,0x3f3504f3,0xbf3504f3,0x3f0e39da,0xbf54db31,
0x3ec3ef15,0xbf6c835e,0x3e47c5c2,0xbf7b14be,0x3f800000,0x0,0x3f7853f8,0xbe78cfcc,0x3f61c598,0xbef15aea,0x3f3daef9,0xbf2beb4a,
0x3f0e39da,0xbf54db31,0x3eac7cd4,0xbf710908,0x3dc8bd36,0xbf7ec46d,0xbe164083,0xbf7d3aac,0x3f800000,0x0,0x3f74fa0b,0xbe94a031,
0x3f54db31,0xbf0e39da,0x3f226799,0xbf45e403,0x3ec3ef15,0xbf6c835e,0x3dc8bd36,0xbf7ec46d,0xbe47c5c2,0xbf7b14be,0xbef15aea,0xbf61c598,
0x3f800000,0x0,0x3f710908,0xbeac7cd4,0x3f45e403,0xbf226799,0x3f039c3d,0xbf5b941a,0x3e47c5c2,0xbf7b14be,0xbe164083,0xbf7d3aac,
0xbef15aea,0xbf61c598,0xbf3daef9,0xbf2beb4a,0x3f800000,0x0,0x3f800000,0x0,0x3f800000,0x0,0x3f800000,0x0,
0x3f800000,0x0,0x3f800000,0x0,0x3f800000,0x0,0x3f800000,0x0,0x3f6c835e,0xbec3ef15,0x3f676bd8,0xbedae880,
0x3f61c598,0xbef15aea,0x3f5b941a,0xbf039c3d,0x3f54db31,0xbf0e39da,0x3f4d9f02,0xbf187fc0,0x3f45e403,0xbf226799,0x3f3daef9,0xbf2beb4a,
0x3f3504f3,0xbf3504f3,0x3f226799,0xbf45e403,0x3f0e39da,0xbf54db31,0x3ef15aea,0xbf61c598,0x3ec3ef15,0xbf6c835e,0x3e94a031,0xbf74fa0b,
0x3e47c5c2,0xbf7b14be,0x3dc8bd36,0xbf7ec46d,0x3ec3ef15,0xbf6c835e,0x3e78cfcc,0xbf7853f8,0x3dc8bd36,0xbf7ec46d,0xbd48fb30,0xbf7fb10f,
0xbe47c5c2,0xbf7b14be,0xbeac7cd4,0xbf710908,0xbef15aea,0xbf61c598,0xbf187fc0,0xbf4d9f02,0x0,0xbf800000,0xbe47c5c2,0xbf7b14be,
0xbec3ef15,0xbf6c835e,0xbf0e39da,0xbf54db31,0xbf3504f3,0xbf3504f3,0xbf54db31,0xbf0e39da,0xbf6c835e,0xbec3ef15,0xbf7b14be,0xbe47c5c2,
0xbec3ef15,0xbf6c835e,0xbf187fc0,0xbf4d9f02,0xbf45e403,0xbf226799,0xbf676bd8,0xbedae880,0xbf7b14be,0xbe47c5c2,0xbf7fb10f,0x3d48fb30,
0xbf74fa0b,0x3e94a031,0xbf5b941a,0x3f039c3d,0xbf3504f3,0xbf3504f3,0xbf61c598,0xbef15aea,0xbf7b14be,0xbe47c5c2,0xbf7ec46d,0x3dc8bd36,
0xbf6c835e,0x3ec3ef15,0xbf45e403,0x3f226799,0xbf0e39da,0x3f54db31,0xbe94a031,0x3f74fa0b,0xbf6c835e,0xbec3ef15,0xbf7fb10f,0xbd48fb30,
0xbf74fa0b,0x3e94a031,0xbf4d9f02,0x3f187fc0,0xbf0e39da,0x3f54db31,0xbe78cfcc,0x3f7853f8,0x3dc8bd36,0x3f7ec46d,0x3edae880,0x3f676bd8,
0x80003f80,0x3f800000,0x3f800000,0xbf80,0x3ec43f6d,0x3f6dbec4,0x3f6dbec4,0xbec4bf6d,0x3f353f35,0x3f35bf35,0x3f35bf35,0xbf35bf35,
0x3f6d3ec4,0x3ec4bf6d,0x3ec4bf6d,0xbf6dbec4,0x80003f80,0x3f800000,0xbf800000,0x3f80,0x3f6d3ec4,0x3ec4bf6d,0xbec43f6d,0x3f6d3ec4,
0x3f35bf35,0xbf35bf35,0x3f353f35,0x3f35bf35,0xbec4bf6d,0xbf6d3ec4,0x3f6dbec4,0xbec4bf6d,0x80003f80,0x3f800000,0x3f800000,0xbf80,
0x3f6dbec4,0xbec4bf6d,0xbec4bf6d,0xbf6d3ec4,0xbf35bf35,0xbf353f35,0xbf353f35,0x3f353f35,0xbec43f6d,0x3f6d3ec4,0x3f6d3ec4,0x3ec4bf6d,
0x80003f80,0x3f800000,0xbf800000,0x3f80,0x3ec4bf6d,0xbf6dbec4,0x3f6d3ec4,0x3ec4bf6d,0xbf353f35,0x3f353f35,0xbf35bf35,0xbf353f35,
0x3f6dbec4,0xbec4bf6d,0x3ec43f6d,0x3f6dbec4,0x80003f80,0x3f800000,0x3f800000,0xbf80,0xbec4bf6d,0xbf6d3ec4,0xbf6d3ec4,0x3ec43f6d,
0x3f353f35,0x3f35bf35,0x3f35bf35,0xbf35bf35,0xbf6dbec4,0xbec43f6d,0xbec43f6d,0x3f6d3ec4,0x80003f80,0x3f800000,0xbf800000,0x3f80,
0xbf6dbec4,0xbec43f6d,0x3ec4bf6d,0xbf6dbec4,0x3f35bf35,0xbf35bf35,0x3f353f35,0x3f35bf35,0x3ec43f6d,0x3f6dbec4,0xbf6d3ec4,0x3ec43f6d,
0x80003f80,0x3f800000,0x3f800000,0xbf80,0xbf6d3ec4,0x3ec43f6d,0x3ec43f6d,0x3f6dbec4,0xbf35bf35,0xbf353f35,0xbf353f35,0x3f353f35,
0x3ec4bf6d,0xbf6dbec4,0xbf6dbec4,0xbec43f6d,0x80003f80,0x3f800000,0xbf800000,0x3f80,0xbec43f6d,0x3f6d3ec4,0xbf6dbec4,0xbec43f6d,
0xbf353f35,0x3f353f35,0xbf35bf35,0xbf353f35,0xbf6d3ec4,0x3ec43f6d,0xbec4bf6d,0xbf6d3ec4,0x3f803f80,0x80008000,0x80008000,0xbf80bf80,
0x3f803f80,0x80008000,0x80008000,0xbf80bf80,0x3f803f80,0x80008000,0x80008000,0xbf80bf80,0x3f803f80,0x80008000,0x80008000,0xbf80bf80,
0x3ec43f6d,0x3f6d3ec4,0x3f6d3ec4,0xbec4bf6d,0xbf6dbec4,0x3ec43f6d,0x3ec43f6d,0x3f6d3ec4,0xbec4bf6d,0xbf6dbec4,0xbf6dbec4,0x3ec43f6d,
0x3f6d3ec4,0xbec4bf6d,0xbec4bf6d,0xbf6dbec4,0xbf353f35,0x3f353f35,0x3f353f35,0x3f35bf35,0x3f35bf35,0xbf35bf35,0xbf35bf35,0xbf353f35,
0xbf353f35,0x3f353f35,0x3f353f35,0x3f35bf35,0x3f35bf35,0xbf35bf35,0xbf35bf35,0xbf353f35,0xbf6d3ec4,0xbec43f6d,0xbec43f6d,0x3f6dbec4,
0xbec43f6d,0x3f6dbec4,0x3f6dbec4,0x3ec4bf6d,0x3f6dbec4,0x3ec4bf6d,0x3ec4bf6d,0xbf6d3ec4,0x3ec4bf6d,0xbf6d3ec4,0xbf6d3ec4,0xbec43f6d,
0x0,0xbf803f80,0xbf803f80,0x80008000,0x0,0xbf803f80,0xbf803f80,0x80008000,0x0,0xbf803f80,0xbf803f80,0x80008000,
0x0,0xbf803f80,0xbf803f80,0x80008000,0x3f6dbec4,0xbec43f6d,0xbec43f6d,0xbf6d3ec4,0x3ec4bf6d,0x3f6dbec4,0x3f6dbec4,0xbec43f6d,
0xbf6d3ec4,0x3ec4bf6d,0x3ec4bf6d,0x3f6dbec4,0xbec43f6d,0xbf6d3ec4,0xbf6d3ec4,0x3ec4bf6d,0x3f35bf35,0x3f353f35,0x3f353f35,0xbf353f35,
0xbf353f35,0xbf35bf35,0xbf35bf35,0x3f35bf35,0x3f35bf35,0x3f353f35,0x3f353f35,0xbf353f35,0xbf353f35,0xbf35bf35,0xbf35bf35,0x3f35bf35,
0xbec4bf6d,0x3f6d3ec4,0x3f6d3ec4,0x3ec43f6d,0x3f6d3ec4,0x3ec43f6d,0x3ec43f6d,0xbf6dbec4,0x3ec43f6d,0xbf6dbec4,0xbf6dbec4,0xbec4bf6d,
0xbf6dbec4,0xbec4bf6d,0xbec4bf6d,0x3f6d3ec4,0x3f800000,0x0,0x3f7fec43,0xbcc90ab0,0x3f7fb10f,0xbd48fb30,0x3f7f4e6d,0xbd96a905,
0x3f7ec46d,0xbdc8bd36,0x3f7e1324,0xbdfab273,0x3f7d3aac,0xbe164083,0x3f7c3b28,0xbe2f10a2,0x3f800000,0x0,0x3f7f4e6d,0xbd96a905,
0x3f7d3aac,0xbe164083,0x3f79c79d,0xbe605c13,0x3f74fa0b,0xbe94a031,0x3f6ed89e,0xbeb8442a,0x3f676bd8,0xbedae880,0x3f5ebe05,0xbefc5d27,
0x3f800000,0x0,0x3f7e1324,0xbdfab273,0x3f7853f8,0xbe78cfcc,0x3f6ed89e,0xbeb8442a,0x3f61c598,0xbef15aea,0x3f514d3d,0xbf13682a,
0x3f3daef9,0xbf2beb4a,0x3f273656,0xbf41d870,0x3f800000,0x0,0x3f7c3b28,0xbe2f10a2,0x3f710908,0xbeac7cd4,0x3f5ebe05,0xbefc5d27,
0x3f45e403,0xbf226799,0x3f273656,0xbf41d870,0x3f039c3d,0xbf5b941a,0x3eb8442a,0xbf6ed89e,0x3f800000,0x0,0x3f79c79d,0xbe605c13,
0x3f676bd8,0xbedae880,0x3f49d112,0xbf1d7fd1,0x3f226799,0xbf45e403,0x3ee63375,0xbf64aa59,0x3e78cfcc,0xbf7853f8,0x3cc90ab0,0xbf7fec43,
0x3f800000,0x0,0x3f76ba07,0xbe888e93,0x3f5b941a,0xbf039c3d,0x3f3085bb,0xbf396842,0x3ef15aea,0xbf61c598,0x3e605c13,0xbf79c79d,
0xbd48fb30,0xbf7fb10f,0xbea09ae5,0xbf731447,0x3f800000,0x0,0x3f731447,0xbea09ae5,0x3f4d9f02,0xbf187fc0,0x3f13682a,0xbf514d3d,
0x3e94a031,0xbf74fa0b,0xbcc90ab0,0xbf7fec43,0xbeac7cd4,0xbf710908,0xbf1d7fd1,0xbf49d112,0x3f800000,0x0,0x3f6ed89e,0xbeb8442a,
0x3f3daef9,0xbf2beb4a,0x3ee63375,0xbf64aa59,0x3dc8bd36,0xbf7ec46d,0xbe888e93,0xbf76ba07,0xbf187fc0,0xbf4d9f02,0xbf584853,0xbf08f59b,
0x3f7b14be,0xbe47c5c2,0x3f79c79d,0xbe605c13,0x3f7853f8,0xbe78cfcc,0x3f76ba07,0xbe888e93,0x3f74fa0b,0xbe94a031,0x3f731447,0xbea09ae5,
0x3f710908,0xbeac7cd4,0x3f6ed89e,0xbeb8442a,0x3f54db31,0xbf0e39da,0x3f49d112,0xbf1d7fd1,0x3f3daef9,0xbf2beb4a,0x3f3085bb,0xbf396842,
0x3f226799,0xbf45e403,0x3f13682a,0xbf514d3d,0x3f039c3d,0xbf5b941a,0x3ee63375,0xbf64aa59,0x3f0e39da,0xbf54db31,0x3ee63375,0xbf64aa59,
0x3eac7cd4,0xbf710908,0x3e605c13,0xbf79c79d,0x3dc8bd36,0xbf7ec46d,0xbcc90ab0,0xbf7fec43,0xbe164083,0xbf7d3aac,0xbe888e93,0xbf76ba07,
0x3e47c5c2,0xbf7b14be,0x3cc90ab0,0xbf7fec43,0xbe164083,0xbf7d3aac,0xbea09ae5,0xbf731447,0xbef15aea,0xbf61c598,0xbf1d7fd1,0xbf49d112,
0xbf3daef9,0xbf2beb4a,0xbf584853,0xbf08f59b,0xbe47c5c2,0xbf7b14be,0xbecf7bca,0xbf6a09a7,0xbf187fc0,0xbf4d9f02,0xbf41d870,0xbf273656,
0xbf61c598,0xbef15aea,0xbf76ba07,0xbe888e93,0xbf7fb10f,0xbd48fb30,0xbf7c3b28,0x3e2f10a2,0xbf0e39da,0xbf54db31,0xbf41d870,0xbf273656,
0xbf676bd8,0xbedae880,0xbf7c3b28,0xbe2f10a2,0xbf7ec46d,0x3dc8bd36,0xbf6ed89e,0x3eb8442a,0xbf4d9f02,0x3f187fc0,0xbf1d7fd1,0x3f49d112,
0xbf54db31,0xbf0e39da,0xbf76ba07,0xbe888e93,0xbf7fb10f,0x3d48fb30,0xbf6ed89e,0x3eb8442a,0xbf45e403,0x3f226799,0xbf08f59b,0x3f584853,
0xbe78cfcc,0x3f7853f8,0x3d96a905,0x3f7f4e6d,0xbf7b14be,0xbe47c5c2,0xbf7c3b28,0x3e2f10a2,0xbf5b941a,0x3f039c3d,0xbf1d7fd1,0x3f49d112,
0xbe94a031,0x3f74fa0b,0x3d96a905,0x3f7f4e6d,0x3edae880,0x3f676bd8,0x3f396842,0x3f3085bb,0x80003f80,0x80003f80,0x80003f80,0x80003f80,
0x80003f80,0x80003f80,0x80003f80,0x80003f80,0x80003f80,0x80003f80,0x80003f80,0x80003f80,0x80003f80,0x80003f80,0x80003f80,0x80003f80,
0x3f800000,0x3f800000,0x3f800000,0x3f800000,0x3f800000,0x3f800000,0x3f800000,0x3f800000,0x3f800000,0x3f800000,0x3f800000,0x3f800000,
0x3f800000,0x3f800000,0x3f800000,0x3f800000,0x80003f80,0x3f353f35,0x80003f80,0x3f353f35,0x3f800000,0x3f35bf35,0x3f800000,0x3f35bf35,
0x8000bf80,0xbf35bf35,0x8000bf80,0xbf35bf35,0xbf800000,0xbf353f35,0xbf800000,0xbf353f35,0x3f800000,0x3f35bf35,0x3f800000,0x3f35bf35,
0xbf80,0xbf35bf35,0xbf80,0xbf35bf35,0xbf800000,0xbf353f35,0xbf800000,0xbf353f35,0x3f80,0x3f353f35,0x3f80,0x3f353f35,
0x80003f80,0x3f800000,0x80003f80,0x3f800000,0x8000bf80,0xbf800000,0x8000bf80,0xbf800000,0x80003f80,0x3f800000,0x80003f80,0x3f800000,
0x8000bf80,0xbf800000,0x8000bf80,0xbf800000,0x3f800000,0xbf80,0x3f800000,0xbf80,0xbf800000,0x3f80,0xbf800000,0x3f80,
0x3f800000,0xbf80,0x3f800000,0xbf80,0xbf800000,0x3f80,0xbf800000,0x3f80,0x80003f80,0x3f35bf35,0x80003f80,0x3f35bf35,
0xbf800000,0x3f353f35,0xbf800000,0x3f353f35,0x8000bf80,0xbf353f35,0x8000bf80,0xbf353f35,0x3f800000,0xbf35bf35,0x3f800000,0xbf35bf35,
0x3f800000,0xbf35bf35,0x3f800000,0xbf35bf35,0x3f80,0x3f35bf35,0x3f80,0x3f35bf35,0xbf800000,0x3f353f35,0xbf800000,0x3f353f35,
0xbf80,0xbf353f35,0xbf80,0xbf353f35,0x80003f80,0x3ec43f6d,0x8000bf80,0xbec4bf6d,0x3f353f35,0x3f6d3ec4,0xbf35bf35,0xbf6dbec4,
0x3f800000,0x3f6dbec4,0xbf800000,0xbf6d3ec4,0x3f35bf35,0x3ec4bf6d,0xbf353f35,0xbec43f6d,0x3f800000,0x3f6dbec4,0xbf800000,0xbf6d3ec4,
0x3f35bf35,0x3ec4bf6d,0xbf353f35,0xbec43f6d,0xbf80,0xbec4bf6d,0x3f80,0x3ec43f6d,0xbf35bf35,0xbf6dbec4,0x3f353f35,0x3f6d3ec4,
0x80003f80,0x3f6d3ec4,0x8000bf80,0xbf6dbec4,0x3f35bf35,0xbec4bf6d,0xbf353f35,0x3ec43f6d,0xbf800000,0xbec43f6d,0x3f800000,0x3ec4bf6d,
0x3f353f35,0x3f6dbec4,0xbf35bf35,0xbf6d3ec4,0x3f800000,0x3ec4bf6d,0xbf800000,0xbec43f6d,0xbf35bf35,0xbf6d3ec4,0x3f353f35,0x3f6dbec4,
0x3f80,0x3f6d3ec4,0xbf80,0xbf6dbec4,0x3f35bf35,0xbec4bf6d,0xbf353f35,0x3ec43f6d,0x80003f80,0x3f6dbec4,0x8000bf80,0xbf6d3ec4,
0xbf35bf35,0xbec43f6d,0x3f353f35,0x3ec4bf6d,0x3f800000,0xbec4bf6d,0xbf800000,0x3ec43f6d,0xbf353f35,0x3f6d3ec4,0x3f35bf35,0xbf6dbec4,
0x3f800000,0xbec4bf6d,0xbf800000,0x3ec43f6d,0xbf353f35,0x3f6d3ec4,0x3f35bf35,0xbf6dbec4,0xbf80,0xbf6d3ec4,0x3f80,0x3f6dbec4,
0x3f353f35,0x3ec4bf6d,0xbf35bf35,0xbec43f6d,0x80003f80,0x3ec4bf6d,0x8000bf80,0xbec43f6d,0xbf353f35,0x3f6dbec4,0x3f35bf35,0xbf6d3ec4,
0xbf800000,0x3f6d3ec4,0x3f800000,0xbf6dbec4,0xbf35bf35,0x3ec43f6d,0x3f353f35,0xbec4bf6d,0x3f800000,0xbf6dbec4,0xbf800000,0x3f6d3ec4,
0x3f353f35,0xbec4bf6d,0xbf35bf35,0x3ec43f6d,0x3f80,0x3ec4bf6d,0xbf80,0xbec43f6d,0xbf353f35,0x3f6dbec4,0x3f35bf35,0xbf6d3ec4,
0x80003f80,0x8000bf80,0x80003f80,0x8000bf80,0x80003f80,0x8000bf80,0x80003f80,0x8000bf80,0x80003f80,0x8000bf80,0x80003f80,0x8000bf80,
0x80003f80,0x8000bf80,0x80003f80,0x8000bf80,0x3f800000,0xbf800000,0x3f800000,0xbf800000,0x3f800000,0xbf800000,0x3f800000,0xbf800000,
0x3f800000,0xbf800000,0x3f800000,0xbf800000,0x3f800000,0xbf800000,0x3f800000,0xbf800000,0x80003f80,0xbf35bf35,0x80003f80,0xbf35bf35,
0x3f800000,0xbf353f35,0x3f800000,0xbf353f35,0x8000bf80,0x3f353f35,0x8000bf80,0x3f353f35,0xbf800000,0x3f35bf35,0xbf800000,0x3f35bf35,
0x3f800000,0xbf353f35,0x3f800000,0xbf353f35,0xbf80,0x3f353f35,0xbf80,0x3f353f35,0xbf800000,0x3f35bf35,0xbf800000,0x3f35bf35,
0x3f80,0xbf35bf35,0x3f80,0xbf35bf35,0x80003f80,0xbf800000,0x80003f80,0xbf800000,0x8000bf80,0x3f800000,0x8000bf80,0x3f800000,
0x80003f80,0xbf800000,0x80003f80,0xbf800000,0x8000bf80,0x3f800000,0x8000bf80,0x3f800000,0x3f800000,0x3f80,0x3f800000,0x3f80,
0xbf800000,0xbf80,0xbf800000,0xbf80,0x3f800000,0x3f80,0x3f800000,0x3f80,0xbf800000,0xbf80,0xbf800000,0xbf80,
0x80003f80,0xbf353f35,0x80003f80,0xbf353f35,0xbf800000,0xbf35bf35,0xbf800000,0xbf35bf35,0x8000bf80,0x3f35bf35,0x8000bf80,0x3f35bf35,
0x3f800000,0x3f353f35,0x3f800000,0x3f353f35,0x3f800000,0x3f353f35,0x3f800000,0x3f353f35,0x3f80,0xbf353f35,0x3f80,0xbf353f35,
0xbf800000,0xbf35bf35,0xbf800000,0xbf35bf35,0xbf80,0x3f35bf35,0xbf80,0x3f35bf35,0x80003f80,0xbec4bf6d,0x8000bf80,0x3ec43f6d,
0x3f353f35,0xbf6dbec4,0xbf35bf35,0x3f6d3ec4,0x3f800000,0xbf6d3ec4,0xbf800000,0x3f6dbec4,0x3f35bf35,0xbec43f6d,0xbf353f35,0x3ec4bf6d,
0x3f800000,0xbf6d3ec4,0xbf800000,0x3f6dbec4,0x3f35bf35,0xbec43f6d,0xbf353f35,0x3ec4bf6d,0xbf80,0x3ec43f6d,0x3f80,0xbec4bf6d,
0xbf35bf35,0x3f6d3ec4,0x3f353f35,0xbf6dbec4,0x80003f80,0xbf6dbec4,0x8000bf80,0x3f6d3ec4,0x3f35bf35,0x3ec43f6d,0xbf353f35,0xbec4bf6d,
0xbf800000,0x3ec4bf6d,0x3f800000,0xbec43f6d,0x3f353f35,0xbf6d3ec4,0xbf35bf35,0x3f6dbec4,0x3f800000,0xbec43f6d,0xbf800000,0x3ec4bf6d,
0xbf35bf35,0x3f6dbec4,0x3f353f35,0xbf6d3ec4,0x3f80,0xbf6dbec4,0xbf80,0x3f6d3ec4,0x3f35bf35,0x3ec43f6d,0xbf353f35,0xbec4bf6d,
0x80003f80,0xbf6d3ec4,0x8000bf80,0x3f6dbec4,0xbf35bf35,0x3ec4bf6d,0x3f353f35,0xbec43f6d,0x3f800000,0x3ec43f6d,0xbf800000,0xbec4bf6d,
0xbf353f35,0xbf6dbec4,0x3f35bf35,0x3f6d3ec4,0x3f800000,0x3ec43f6d,0xbf800000,0xbec4bf6d,0xbf353f35,0xbf6dbec4,0x3f35bf35,0x3f6d3ec4,
0xbf80,0x3f6dbec4,0x3f80,0xbf6d3ec4,0x3f353f35,0xbec43f6d,0xbf35bf35,0x3ec4bf6d,0x80003f80,0xbec43f6d,0x8000bf80,0x3ec4bf6d,
0xbf353f35,0xbf6d3ec4,0x3f35bf35,0x3f6dbec4,0xbf800000,0xbf6dbec4,0x3f800000,0x3f6d3ec4,0xbf35bf35,0xbec4bf6d,0x3f353f35,0x3ec43f6d,
0x3f800000,0x3f6d3ec4,0xbf800000,0xbf6dbec4,0x3f353f35,0x3ec43f6d,0xbf35bf35,0xbec4bf6d,0x3f80,0xbec43f6d,0xbf80,0x3ec4bf6d,
0xbf353f35,0xbf6d3ec4,0x3f35bf35,0x3f6dbec4,
};
constexpr int TB_F = 0, TB_E = 512, TB_P2 = 1024;

enum { C_EP = 0, C_Z1 = 32, C_Z2 = 96, C_H3 = 128, C_U = 160, C_X = 256, C_TOTAL = 512 };
struct Scratch {
  unsigned cnt[C_TOTAL];
  uint32_t moda[8 * 2 * D_];
  uint32_t mod[4 * D_ + 256];
  uint32_t z1[120 * 5120];
  uint32_t z2[128 * 4800];
  uint32_t x1[S_ * D_ / 2];
  uint8_t h3[32 * 18 * 4096];
  uint8_t u[72 * D_ * 128];
  uint4 part[128 * 1152];
};
__device__ __align__(1024) Scratch g_s;

#define PF2 8
#define PF2K 16
#define HOLDA 6
#define GOAT 0
#define HOLD1 1
#define HW bulk_commit_wait
#define H3W 0
#define X1K 10
#define PEEK 1
#define H3G 1
#define PFF 2
#define WAITALL 0
#ifndef NV1
#define NV1 12
#endif
#ifndef NV2
#define NV2 16
#endif
#define WARM 0
#define GDEP 0
#define TRKB 2048
#define TRKC 250
#define NG1 2

#define FAILCNT(k) do {} while (0)
#define CK(k) do {} while (0)
#define CKX(k) do {} while (0)
#define TS(k) do {} while (0)
#define TSC(k) do {} while (0)
struct Maps { CUtensorMap z1, z2[2], w1a, w1b, h3[2], w2, x1, out, wf[4], wm; };
struct Params {
  const __nv_bfloat16 *x, *c, *wmod;
  Scratch* s;
  const uint4* tab;
  const __nv_bfloat16 *wr, *wi, *w1, *w2, *b1, *b2;
};

__device__ __forceinline__ uint32_t smem_u32(const void* p) { return (uint32_t)__cvta_generic_to_shared(p); }
__device__ __forceinline__ void mbar_init(uint32_t b, int c) { asm volatile("mbarrier.init.shared::cta.b64 [%0], %1;" ::"r"(b), "r"(c)); }
__device__ __forceinline__ void mbar_expect(uint32_t b, int bytes) { asm volatile("mbarrier.arrive.expect_tx.shared::cta.b64 _, [%0], %1;" ::"r"(b), "r"(bytes) : "memory"); }
__device__ __forceinline__ void mbar_arrive(uint32_t b) { asm volatile("mbarrier.arrive.shared::cta.b64 _, [%0];" ::"r"(b) : "memory"); }
#define MBAR_WAIT(SEM)                                                                                                         \
  asm volatile("{\n.reg .pred p;\n.reg .u32 it;\nmov.u32 it, 0;\nW:\nmbarrier.try_wait.parity" SEM ".shared::cta.b64 p, [%0], %1;\n" \
               "@p bra.uni D;\nadd.u32 it, it, 1;\nsetp.lt.u32 p, it, 0x400000;\n@p bra.uni W;\ntrap;\nD:\n}" ::"r"(b), "r"(ph) : "memory")
__device__ __forceinline__ void mbar_wait(uint32_t b, int ph) { MBAR_WAIT(""); }
__device__ __forceinline__ uint32_t mbar_test(uint32_t b, int ph) {
  uint32_t ok;
  asm volatile("{\n.reg .pred p;\nmbarrier.test_wait.parity.shared::cta.b64 p, [%1], %2;\nselp.u32 %0, 1, 0, p;\n}\n" : "=r"(ok) : "r"(b), "r"(ph) : "memory");
  return ok;
}
__device__ __forceinline__ void tma2d(uint32_t dst, const CUtensorMap* m, int c0, int c1, uint32_t bar) {
  asm volatile("cp.async.bulk.tensor.2d.shared::cluster.global.mbarrier::complete_tx::bytes [%0], [%1, {%3, %4}], [%2];" ::"r"(dst), "l"(m), "r"(bar), "r"(c0), "r"(c1) : "memory");
}
__device__ __forceinline__ uint64_t pol_ef() { uint64_t p; asm("createpolicy.fractional.L2::evict_first.b64 %0, 1.0;" : "=l"(p)); return p; }
__device__ __forceinline__ void tma3d_ef(uint32_t dst, const CUtensorMap* m, int c1, int c2, uint32_t bar) {
  asm volatile("cp.async.bulk.tensor.3d.shared::cluster.global.mbarrier::complete_tx::bytes.L2::cache_hint [%0], [%1, {%3, %4, %5}], [%2], %6;" ::"r"(dst), "l"(m), "r"(bar), "r"(0), "r"(c1), "r"(c2), "l"(pol_ef()) : "memory");
}
__device__ __forceinline__ void tma4d_ef(uint32_t dst, const CUtensorMap* m, int c1, int c2, int c3, uint32_t bar) {
  asm volatile("cp.async.bulk.tensor.4d.shared::cluster.global.mbarrier::complete_tx::bytes.L2::cache_hint [%0], [%1, {%3, %7, %4, %5}], [%2], %6;" ::"r"(dst), "l"(m), "r"(bar), "r"(0), "r"(c2), "r"(c3), "l"(pol_ef()), "r"(c1) : "memory");
}
__device__ __forceinline__ void bulk_ld(uint32_t dst, const void* src, int bytes, uint32_t bar) {
  asm volatile("cp.async.bulk.shared::cluster.global.mbarrier::complete_tx::bytes [%0], [%1], %2, [%3];" ::"r"(dst), "l"(src), "r"(bytes), "r"(bar) : "memory");
}
__device__ __forceinline__ void bulk_st(void* dst, uint32_t src, int bytes) {
  asm volatile("cp.async.bulk.global.shared::cta.bulk_group [%0], [%1], %2;" ::"l"(dst), "r"(src), "r"(bytes) : "memory");
}
__device__ __forceinline__ void tma_st2d(const CUtensorMap* m, uint32_t src, int c0, int c1) {
  asm volatile("cp.async.bulk.tensor.2d.global.shared::cta.bulk_group [%0, {%2, %3}], [%1];" ::"l"(m), "r"(src), "r"(c0), "r"(c1) : "memory");
}
__device__ __forceinline__ void tma_st3d(const CUtensorMap* m, uint32_t src, int c0, int c1, int c2) {
  asm volatile("cp.async.bulk.tensor.3d.global.shared::cta.bulk_group [%0, {%2, %3, %4}], [%1];" ::"l"(m), "r"(src), "r"(c0), "r"(c1), "r"(c2) : "memory");
}
__device__ __forceinline__ void bulk_commit_wait_read() {
  asm volatile("cp.async.bulk.commit_group;" ::: "memory");
  asm volatile("cp.async.bulk.wait_group.read 0;" ::: "memory");
}
__device__ __forceinline__ void bulk_commit_wait() {
  asm volatile("cp.async.bulk.commit_group;" ::: "memory");
  asm volatile("cp.async.bulk.wait_group 0;" ::: "memory");
}
__device__ __forceinline__ void prefetch_l2(const void* p, int bytes) {
  asm volatile("cp.async.bulk.prefetch.L2.global [%0], %1;" ::"l"(p), "r"(bytes) : "memory");
}
__device__ __forceinline__ void wg_fence() { asm volatile("wgmma.fence.sync.aligned;" ::: "memory"); }
__device__ __forceinline__ void wg_commit() { asm volatile("wgmma.commit_group.sync.aligned;" ::: "memory"); }
template <int N> __device__ __forceinline__ void wg_wait() { asm volatile("wgmma.wait_group.sync.aligned %0;" ::"n"(N) : "memory"); }
template <int N> __device__ __forceinline__ void reg_fence(float (&d)[N]) {
#pragma unroll
  for (int i = 0; i < N; i++) asm volatile("" : "+f"(d[i])::"memory");
}
__device__ __forceinline__ void fence_async_smem() { asm volatile("fence.proxy.async.shared::cta;" ::: "memory"); }
__device__ __forceinline__ void fence_async_glb() { asm volatile("fence.proxy.async.global;" ::: "memory"); }
__device__ __forceinline__ uint32_t ld_rlx(const void* p) { uint32_t v; asm volatile("ld.relaxed.gpu.global.b32 %0, [%1];" : "=r"(v) : "l"(p) : "memory"); return v; }
__device__ __forceinline__ uint2 ld_rlx2(const void* p) { uint2 v; asm volatile("ld.relaxed.gpu.global.v2.b32 {%0,%1}, [%2];" : "=r"(v.x), "=r"(v.y) : "l"(p) : "memory"); return v; }
__device__ __forceinline__ uint4 ld_rlx4(const void* p) { uint4 v; asm volatile("ld.relaxed.gpu.global.v4.b32 {%0,%1,%2,%3}, [%4];" : "=r"(v.x), "=r"(v.y), "=r"(v.z), "=r"(v.w) : "l"(p) : "memory"); return v; }
__device__ __forceinline__ uint32_t ld_nc(const void* p) { uint32_t v; asm volatile("ld.global.nc.L1::no_allocate.b32 %0, [%1];" : "=r"(v) : "l"(p) : "memory"); return v; }
__device__ __forceinline__ uint4 ld_nc4(const void* p) { uint4 v; asm volatile("ld.global.nc.v4.b32 {%0,%1,%2,%3}, [%4];" : "=r"(v.x), "=r"(v.y), "=r"(v.z), "=r"(v.w) : "l"(p) : "memory"); return v; }
__device__ __forceinline__ uint32_t lds(uint32_t a) { uint32_t v; asm volatile("ld.shared.b32 %0, [%1];" : "=r"(v) : "r"(a) : "memory"); return v; }
__device__ __forceinline__ uint2 lds2(uint32_t a) { uint2 v; asm volatile("ld.shared.v2.b32 {%0,%1}, [%2];" : "=r"(v.x), "=r"(v.y) : "r"(a) : "memory"); return v; }
__device__ __forceinline__ uint4 lds4(uint32_t a) { uint4 v; asm volatile("ld.shared.v4.b32 {%0,%1,%2,%3}, [%4];" : "=r"(v.x), "=r"(v.y), "=r"(v.z), "=r"(v.w) : "r"(a) : "memory"); return v; }
__device__ __forceinline__ float lds_bf(uint32_t a) { uint32_t v; asm volatile("ld.shared.u16 %0, [%1];" : "=r"(v) : "r"(a) : "memory"); return __uint_as_float(v << 16); }
__device__ __forceinline__ void sts(uint32_t a, uint32_t v) { asm volatile("st.shared.b32 [%0], %1;" ::"r"(a), "r"(v) : "memory"); }
__device__ __forceinline__ void sts2(uint32_t a, uint32_t v0, uint32_t v1) { asm volatile("st.shared.v2.b32 [%0], {%1,%2};" ::"r"(a), "r"(v0), "r"(v1) : "memory"); }
__device__ __forceinline__ void sts4(uint32_t a, uint32_t v0, uint32_t v1, uint32_t v2, uint32_t v3) { asm volatile("st.shared.v4.b32 [%0], {%1,%2,%3,%4};" ::"r"(a), "r"(v0), "r"(v1), "r"(v2), "r"(v3) : "memory"); }
__device__ __forceinline__ void bar_sync(int id, int n) { asm volatile("bar.sync %0, %1;" ::"r"(id), "r"(n) : "memory"); }
__device__ __forceinline__ void bar_arrive(int id, int n) { asm volatile("bar.arrive %0, %1;" ::"r"(id), "r"(n) : "memory"); }
__device__ __forceinline__ void red_add(unsigned* p, unsigned v) { asm volatile("red.relaxed.gpu.global.add.u32 [%0], %1;" ::"l"(p), "r"(v) : "memory"); }
__device__ __forceinline__ bool any(bool p) { return __any_sync(0xffffffffu, p); }
__device__ __forceinline__ void pause(unsigned clks) {
  asm volatile("{\n.reg .pred p;\n.reg .u32 a, b;\nmov.u32 a, %%clock;\nW:\nmov.u32 b, %%clock;\nsub.u32 b, b, a;\nsetp.lt.s32 p, b, %0;\n@p bra.uni W;\n}" ::"r"(clks) : "memory");
}
constexpr int SPIN_MAX = 1 << 20;
__device__ __forceinline__ void wait_cnt(const unsigned* p, unsigned target) {
  int it = 0;
  while (any((int)(ld_rlx(p) - target) < 0) && ++it < SPIN_MAX) {}
}
__device__ __forceinline__ uint32_t pack_bf16(float lo, float hi) { uint32_t r; asm("cvt.rn.bf16x2.f32 %0, %1, %2;" : "=r"(r) : "f"(hi), "f"(lo)); return r; }
__device__ __forceinline__ float bf_lo(uint32_t v) { return __uint_as_float(v << 16); }
__device__ __forceinline__ float bf_hi(uint32_t v) { return __uint_as_float(v & 0xffff0000u); }
__device__ __forceinline__ uint32_t hadd2(uint32_t a, uint32_t b) { uint32_t r; asm("add.rn.bf16x2 %0, %1, %2;" : "=r"(r) : "r"(a), "r"(b)); return r; }
__device__ __forceinline__ uint32_t hmul2(uint32_t a, uint32_t b) { uint32_t r; asm("mul.rn.bf16x2 %0, %1, %2;" : "=r"(r) : "r"(a), "r"(b)); return r; }
__device__ __forceinline__ uint32_t hfma2(uint32_t a, uint32_t b, uint32_t c) { uint32_t r; asm("fma.rn.bf16x2 %0, %1, %2, %3;" : "=r"(r) : "r"(a), "r"(b), "r"(c)); return r; }
__device__ __forceinline__ float rbf(float x) { uint32_t r; asm("cvt.rn.bf16x2.f32 %0, %1, %2;" : "=r"(r) : "f"(x), "f"(0.0f)); return __uint_as_float(r); }
__device__ __forceinline__ void stmatrix4(uint32_t a, uint32_t r0, uint32_t r1, uint32_t r2, uint32_t r3) {
  asm volatile("stmatrix.sync.aligned.m8n8.x4.shared.b16 [%0], {%1,%2,%3,%4};" ::"r"(a), "r"(r0), "r"(r1), "r"(r2), "r"(r3) : "memory");
}
__device__ __forceinline__ void stmatrix2(uint32_t a, uint32_t r0, uint32_t r1) {
  asm volatile("stmatrix.sync.aligned.m8n8.x2.shared.b16 [%0], {%1,%2};" ::"r"(a), "r"(r0), "r"(r1) : "memory");
}
__device__ __forceinline__ void stmatrix4t_if(int on, uint32_t a, uint32_t r0, uint32_t r1, uint32_t r2, uint32_t r3) {
  asm volatile("{\n.reg .pred p;\nsetp.ne.u32 p, %5, 0;\n@p stmatrix.sync.aligned.m8n8.x4.trans.shared.b16 [%0], {%1,%2,%3,%4};\n}" ::"r"(a), "r"(r0), "r"(r1), "r"(r2), "r"(r3), "r"(on) : "memory");
}
__device__ __forceinline__ uint32_t movm(uint32_t a) { uint32_t r; asm("movmatrix.sync.aligned.m8n8.trans.b16 %0, %1;" : "=r"(r) : "r"(a)); return r; }
template <bool ACC> __device__ __forceinline__ void mma16(float* d, uint32_t a0, uint32_t a1, uint32_t a2, uint32_t a3, uint32_t b0, uint32_t b1) {
  if (ACC) asm("mma.sync.aligned.m16n8k16.row.col.f32.bf16.bf16.f32 {%0,%1,%2,%3}, {%4,%5,%6,%7}, {%8,%9}, {%0,%1,%2,%3};"
               : "+f"(d[0]), "+f"(d[1]), "+f"(d[2]), "+f"(d[3]) : "r"(a0), "r"(a1), "r"(a2), "r"(a3), "r"(b0), "r"(b1));
  else asm("mma.sync.aligned.m16n8k16.row.col.f32.bf16.bf16.f32 {%0,%1,%2,%3}, {%4,%5,%6,%7}, {%8,%9}, {%10,%10,%10,%10};"
           : "=f"(d[0]), "=f"(d[1]), "=f"(d[2]), "=f"(d[3]) : "r"(a0), "r"(a1), "r"(a2), "r"(a3), "r"(b0), "r"(b1), "f"(0.f));
}
__device__ __forceinline__ uint32_t pin(uint32_t v) { uint32_t r; asm volatile("shfl.sync.bfly.b32 %0, %1, 0, 31, 0xffffffff;" : "=r"(r) : "r"(v)); return r; }
template <class T> __device__ __forceinline__ T* pin(T* p) {
  const uint64_t a = reinterpret_cast<uint64_t>(p);
  return reinterpret_cast<T*>((uint64_t)pin((uint32_t)a) | ((uint64_t)pin((uint32_t)(a >> 32)) << 32));
}
__device__ __forceinline__ uint32_t upin(uint32_t v) { return __shfl_sync(0xffffffffu, v, 0); }
template <class T> __device__ __forceinline__ T* upin(T* p) {
  const uint64_t a = reinterpret_cast<uint64_t>(p);
  return reinterpret_cast<T*>((uint64_t)upin((uint32_t)a) | ((uint64_t)upin((uint32_t)(a >> 32)) << 32));
}
__device__ __forceinline__ bool elect() {
  uint32_t p;
  asm volatile("{\n.reg .pred P;\nelect.sync _|P, 0xffffffff;\nselp.u32 %0, 1, 0, P;\n}" : "=r"(p));
  return p;
}
__device__ __forceinline__ uint32_t set_tag(uint32_t w, uint32_t tag) { uint32_t r; asm("lop3.b32 %0, %1, 0xfffffffe, %2, 0xea;" : "=r"(r) : "r"(w), "r"(tag)); return r; }
__device__ __forceinline__ uint32_t and_or(uint32_t w, uint32_t a, uint32_t o) { uint32_t r; asm("lop3.b32 %0, %1, %2, %3, 0xea;" : "=r"(r) : "r"(w), "r"(a), "r"(o)); return r; }
__device__ __forceinline__ uint32_t or3(uint32_t a, uint32_t b, uint32_t c) { uint32_t r; asm("lop3.b32 %0, %1, %2, %3, 0xfe;" : "=r"(r) : "r"(a), "r"(b), "r"(c)); return r; }
__device__ __forceinline__ uint32_t diff2(uint32_t a, uint32_t b, uint32_t tag) { uint32_t r; asm("lop3.b32 %0, %1, %2, %3, 0x7e;" : "=r"(r) : "r"(a), "r"(b), "r"(tag)); return r; }
__device__ __forceinline__ float2 cmul(float2 a, float2 b) { return make_float2(a.x * b.x - a.y * b.y, a.x * b.y + a.y * b.x); }

template<int TB> __device__ __forceinline__ void wgmma_ss_160_0(float (&d)[96], uint32_t al, uint32_t ah, uint32_t bl, uint32_t bh) {
  asm volatile("{\n.reg .b64 da, db;\nmov.b64 da, {%80, %81};\nmov.b64 db, {%82, %83};\n"
    "wgmma.mma_async.sync.aligned.m64n160k16.f32.bf16.bf16 {%0,%1,%2,%3,%4,%5,%6,%7,%8,%9,%10,%11,%12,%13,%14,%15,%16,%17,%18,%19,%20,%21,%22,%23,%24,%25,%26,%27,%28,%29,%30,%31,%32,%33,%34,%35,%36,%37,%38,%39,%40,%41,%42,%43,%44,%45,%46,%47,%48,%49,%50,%51,%52,%53,%54,%55,%56,%57,%58,%59,%60,%61,%62,%63,%64,%65,%66,%67,%68,%69,%70,%71,%72,%73,%74,%75,%76,%77,%78,%79}, da, db, 1, 1, 1, 1, %84;\n}\n"
    : "+f"(d[0]),"+f"(d[1]),"+f"(d[2]),"+f"(d[3]),"+f"(d[4]),"+f"(d[5]),"+f"(d[6]),"+f"(d[7]),"+f"(d[8]),"+f"(d[9]),"+f"(d[10]),"+f"(d[11]),"+f"(d[12]),"+f"(d[13]),"+f"(d[14]),"+f"(d[15]),"+f"(d[16]),"+f"(d[17]),"+f"(d[18]),"+f"(d[19]),"+f"(d[20]),"+f"(d[21]),"+f"(d[22]),"+f"(d[23]),"+f"(d[24]),"+f"(d[25]),"+f"(d[26]),"+f"(d[27]),"+f"(d[28]),"+f"(d[29]),"+f"(d[30]),"+f"(d[31]),"+f"(d[32]),"+f"(d[33]),"+f"(d[34]),"+f"(d[35]),"+f"(d[36]),"+f"(d[37]),"+f"(d[38]),"+f"(d[39]),"+f"(d[40]),"+f"(d[41]),"+f"(d[42]),"+f"(d[43]),"+f"(d[44]),"+f"(d[45]),"+f"(d[46]),"+f"(d[47]),"+f"(d[48]),"+f"(d[49]),"+f"(d[50]),"+f"(d[51]),"+f"(d[52]),"+f"(d[53]),"+f"(d[54]),"+f"(d[55]),"+f"(d[56]),"+f"(d[57]),"+f"(d[58]),"+f"(d[59]),"+f"(d[60]),"+f"(d[61]),"+f"(d[62]),"+f"(d[63]),"+f"(d[64]),"+f"(d[65]),"+f"(d[66]),"+f"(d[67]),"+f"(d[68]),"+f"(d[69]),"+f"(d[70]),"+f"(d[71]),"+f"(d[72]),"+f"(d[73]),"+f"(d[74]),"+f"(d[75]),"+f"(d[76]),"+f"(d[77]),"+f"(d[78]),"+f"(d[79])
    : "r"(al), "r"(ah), "r"(bl), "r"(bh), "n"(TB));
}
template<int TB> __device__ __forceinline__ void wgmma_ss_144_0(float (&d)[96], uint32_t al, uint32_t ah, uint32_t bl, uint32_t bh) {
  asm volatile("{\n.reg .b64 da, db;\nmov.b64 da, {%72, %73};\nmov.b64 db, {%74, %75};\n"
    "wgmma.mma_async.sync.aligned.m64n144k16.f32.bf16.bf16 {%0,%1,%2,%3,%4,%5,%6,%7,%8,%9,%10,%11,%12,%13,%14,%15,%16,%17,%18,%19,%20,%21,%22,%23,%24,%25,%26,%27,%28,%29,%30,%31,%32,%33,%34,%35,%36,%37,%38,%39,%40,%41,%42,%43,%44,%45,%46,%47,%48,%49,%50,%51,%52,%53,%54,%55,%56,%57,%58,%59,%60,%61,%62,%63,%64,%65,%66,%67,%68,%69,%70,%71}, da, db, 1, 1, 1, 1, %76;\n}\n"
    : "+f"(d[0]),"+f"(d[1]),"+f"(d[2]),"+f"(d[3]),"+f"(d[4]),"+f"(d[5]),"+f"(d[6]),"+f"(d[7]),"+f"(d[8]),"+f"(d[9]),"+f"(d[10]),"+f"(d[11]),"+f"(d[12]),"+f"(d[13]),"+f"(d[14]),"+f"(d[15]),"+f"(d[16]),"+f"(d[17]),"+f"(d[18]),"+f"(d[19]),"+f"(d[20]),"+f"(d[21]),"+f"(d[22]),"+f"(d[23]),"+f"(d[24]),"+f"(d[25]),"+f"(d[26]),"+f"(d[27]),"+f"(d[28]),"+f"(d[29]),"+f"(d[30]),"+f"(d[31]),"+f"(d[32]),"+f"(d[33]),"+f"(d[34]),"+f"(d[35]),"+f"(d[36]),"+f"(d[37]),"+f"(d[38]),"+f"(d[39]),"+f"(d[40]),"+f"(d[41]),"+f"(d[42]),"+f"(d[43]),"+f"(d[44]),"+f"(d[45]),"+f"(d[46]),"+f"(d[47]),"+f"(d[48]),"+f"(d[49]),"+f"(d[50]),"+f"(d[51]),"+f"(d[52]),"+f"(d[53]),"+f"(d[54]),"+f"(d[55]),"+f"(d[56]),"+f"(d[57]),"+f"(d[58]),"+f"(d[59]),"+f"(d[60]),"+f"(d[61]),"+f"(d[62]),"+f"(d[63]),"+f"(d[64]),"+f"(d[65]),"+f"(d[66]),"+f"(d[67]),"+f"(d[68]),"+f"(d[69]),"+f"(d[70]),"+f"(d[71])
    : "r"(al), "r"(ah), "r"(bl), "r"(bh), "n"(TB));
}
template<int TB> __device__ __forceinline__ void wgmma_ss_96_0(float (&d)[96], uint32_t al, uint32_t ah, uint32_t bl, uint32_t bh) {
  asm volatile("{\n.reg .b64 da, db;\nmov.b64 da, {%48, %49};\nmov.b64 db, {%50, %51};\n"
    "wgmma.mma_async.sync.aligned.m64n96k16.f32.bf16.bf16 {%0,%1,%2,%3,%4,%5,%6,%7,%8,%9,%10,%11,%12,%13,%14,%15,%16,%17,%18,%19,%20,%21,%22,%23,%24,%25,%26,%27,%28,%29,%30,%31,%32,%33,%34,%35,%36,%37,%38,%39,%40,%41,%42,%43,%44,%45,%46,%47}, da, db, 1, 1, 1, 1, %52;\n}\n"
    : "+f"(d[0]),"+f"(d[1]),"+f"(d[2]),"+f"(d[3]),"+f"(d[4]),"+f"(d[5]),"+f"(d[6]),"+f"(d[7]),"+f"(d[8]),"+f"(d[9]),"+f"(d[10]),"+f"(d[11]),"+f"(d[12]),"+f"(d[13]),"+f"(d[14]),"+f"(d[15]),"+f"(d[16]),"+f"(d[17]),"+f"(d[18]),"+f"(d[19]),"+f"(d[20]),"+f"(d[21]),"+f"(d[22]),"+f"(d[23]),"+f"(d[24]),"+f"(d[25]),"+f"(d[26]),"+f"(d[27]),"+f"(d[28]),"+f"(d[29]),"+f"(d[30]),"+f"(d[31]),"+f"(d[32]),"+f"(d[33]),"+f"(d[34]),"+f"(d[35]),"+f"(d[36]),"+f"(d[37]),"+f"(d[38]),"+f"(d[39]),"+f"(d[40]),"+f"(d[41]),"+f"(d[42]),"+f"(d[43]),"+f"(d[44]),"+f"(d[45]),"+f"(d[46]),"+f"(d[47])
    : "r"(al), "r"(ah), "r"(bl), "r"(bh), "n"(TB));
}
template<int TB> __device__ __forceinline__ void wgmma_ss_96_48(float (&d)[96], uint32_t al, uint32_t ah, uint32_t bl, uint32_t bh) {
  asm volatile("{\n.reg .b64 da, db;\nmov.b64 da, {%48, %49};\nmov.b64 db, {%50, %51};\n"
    "wgmma.mma_async.sync.aligned.m64n96k16.f32.bf16.bf16 {%0,%1,%2,%3,%4,%5,%6,%7,%8,%9,%10,%11,%12,%13,%14,%15,%16,%17,%18,%19,%20,%21,%22,%23,%24,%25,%26,%27,%28,%29,%30,%31,%32,%33,%34,%35,%36,%37,%38,%39,%40,%41,%42,%43,%44,%45,%46,%47}, da, db, 1, 1, 1, 1, %52;\n}\n"
    : "+f"(d[48]),"+f"(d[49]),"+f"(d[50]),"+f"(d[51]),"+f"(d[52]),"+f"(d[53]),"+f"(d[54]),"+f"(d[55]),"+f"(d[56]),"+f"(d[57]),"+f"(d[58]),"+f"(d[59]),"+f"(d[60]),"+f"(d[61]),"+f"(d[62]),"+f"(d[63]),"+f"(d[64]),"+f"(d[65]),"+f"(d[66]),"+f"(d[67]),"+f"(d[68]),"+f"(d[69]),"+f"(d[70]),"+f"(d[71]),"+f"(d[72]),"+f"(d[73]),"+f"(d[74]),"+f"(d[75]),"+f"(d[76]),"+f"(d[77]),"+f"(d[78]),"+f"(d[79]),"+f"(d[80]),"+f"(d[81]),"+f"(d[82]),"+f"(d[83]),"+f"(d[84]),"+f"(d[85]),"+f"(d[86]),"+f"(d[87]),"+f"(d[88]),"+f"(d[89]),"+f"(d[90]),"+f"(d[91]),"+f"(d[92]),"+f"(d[93]),"+f"(d[94]),"+f"(d[95])
    : "r"(al), "r"(ah), "r"(bl), "r"(bh), "n"(TB));
}
__device__ __forceinline__ void wgmma_rs_72(float (&d)[36], uint32_t a0, uint32_t a1, uint32_t a2, uint32_t a3, uint32_t bl, uint32_t bh, int sd) {
  asm volatile("{\n.reg .pred p;\n.reg .b64 db;\nsetp.ne.b32 p, %42, 0;\nmov.b64 db, {%40, %41};\n"
    "wgmma.mma_async.sync.aligned.m64n72k16.f32.bf16.bf16 {%0,%1,%2,%3,%4,%5,%6,%7,%8,%9,%10,%11,%12,%13,%14,%15,%16,%17,%18,%19,%20,%21,%22,%23,%24,%25,%26,%27,%28,%29,%30,%31,%32,%33,%34,%35}, {%36,%37,%38,%39}, db, p, 1, 1, 1;\n}\n"
    : "+f"(d[0]),"+f"(d[1]),"+f"(d[2]),"+f"(d[3]),"+f"(d[4]),"+f"(d[5]),"+f"(d[6]),"+f"(d[7]),"+f"(d[8]),"+f"(d[9]),"+f"(d[10]),"+f"(d[11]),"+f"(d[12]),"+f"(d[13]),"+f"(d[14]),"+f"(d[15]),"+f"(d[16]),"+f"(d[17]),"+f"(d[18]),"+f"(d[19]),"+f"(d[20]),"+f"(d[21]),"+f"(d[22]),"+f"(d[23]),"+f"(d[24]),"+f"(d[25]),"+f"(d[26]),"+f"(d[27]),"+f"(d[28]),"+f"(d[29]),"+f"(d[30]),"+f"(d[31]),"+f"(d[32]),"+f"(d[33]),"+f"(d[34]),"+f"(d[35])
    : "r"(a0), "r"(a1), "r"(a2), "r"(a3), "r"(bl), "r"(bh), "r"(sd));
}
__device__ __forceinline__ void wgmma_rs_48(float (&d)[24], uint32_t a0, uint32_t a1, uint32_t a2, uint32_t a3, uint32_t bl, uint32_t bh, int sd) {
  asm volatile("{\n.reg .pred p;\n.reg .b64 db;\nsetp.ne.b32 p, %30, 0;\nmov.b64 db, {%28, %29};\n"
    "wgmma.mma_async.sync.aligned.m64n48k16.f32.bf16.bf16 {%0,%1,%2,%3,%4,%5,%6,%7,%8,%9,%10,%11,%12,%13,%14,%15,%16,%17,%18,%19,%20,%21,%22,%23}, {%24,%25,%26,%27}, db, p, 1, 1, 1;\n}\n"
    : "+f"(d[0]),"+f"(d[1]),"+f"(d[2]),"+f"(d[3]),"+f"(d[4]),"+f"(d[5]),"+f"(d[6]),"+f"(d[7]),"+f"(d[8]),"+f"(d[9]),"+f"(d[10]),"+f"(d[11]),"+f"(d[12]),"+f"(d[13]),"+f"(d[14]),"+f"(d[15]),"+f"(d[16]),"+f"(d[17]),"+f"(d[18]),"+f"(d[19]),"+f"(d[20]),"+f"(d[21]),"+f"(d[22]),"+f"(d[23])
    : "r"(a0), "r"(a1), "r"(a2), "r"(a3), "r"(bl), "r"(bh), "r"(sd));
}
template<int N,int OFF,int TB> __device__ __forceinline__ void wgmma_ss(float (&d)[96], uint32_t al, uint32_t ah, uint32_t bl, uint32_t bh) {
  if constexpr (N==160 && OFF==0) wgmma_ss_160_0<TB>(d, al, ah, bl, bh);
  else if constexpr (N==144 && OFF==0) wgmma_ss_144_0<TB>(d, al, ah, bl, bh);
  else if constexpr (N==96 && OFF==0) wgmma_ss_96_0<TB>(d, al, ah, bl, bh);
  else if constexpr (N==96 && OFF==48) wgmma_ss_96_48<TB>(d, al, ah, bl, bh);
}

__device__ __forceinline__ void dft3(float2& a, float2& b, float2& c) {
  const float s = 0.86602540378443864676f;
  float2 t = make_float2(b.x + c.x, b.y + c.y), d = make_float2(b.x - c.x, b.y - c.y);
  float2 m = make_float2(fmaf(-0.5f, t.x, a.x), fmaf(-0.5f, t.y, a.y));
  a = make_float2(a.x + t.x, a.y + t.y);
  b = make_float2(fmaf(s, d.y, m.x), fmaf(-s, d.x, m.y));
  c = make_float2(fmaf(-s, d.y, m.x), fmaf(s, d.x, m.y));
}
__device__ __forceinline__ void dft9(float2 (&x)[9]) {
  const float2 w1 = make_float2(0.76604444311897803520f, -0.64278760968653932632f);
  const float2 w2 = make_float2(0.17364817766693034885f, -0.98480775301220805937f);
  const float2 w4 = make_float2(-0.93969262078590838405f, -0.34202014332566873304f);
  dft3(x[0], x[3], x[6]); dft3(x[1], x[4], x[7]); dft3(x[2], x[5], x[8]);
  x[4] = cmul(x[4], w1); x[7] = cmul(x[7], w2); x[5] = cmul(x[5], w2); x[8] = cmul(x[8], w4);
  dft3(x[0], x[1], x[2]); dft3(x[3], x[4], x[5]); dft3(x[6], x[7], x[8]);
  float2 t;
  t = x[1]; x[1] = x[3]; x[3] = t;
  t = x[2]; x[2] = x[6]; x[6] = t;
  t = x[5]; x[5] = x[7]; x[7] = t;
}

__device__ __forceinline__ uint32_t* mod_ptr(Scratch* sc, int u, int t128) {
  const int i = t128 & 15;
  return u < 72 ? sc->moda + (t128 >> 4) * (2 * D_) + 16 * u + 2 * (i & 7) + (i >> 3) : sc->mod + 16 * (u - 72) + i;
}
__device__ __forceinline__ void mod_unit(Scratch* sc, int u, int t128, uint32_t sw_, uint32_t bar, int ph, uint32_t rb, uint32_t tag) {
  const int w = t128 >> 5, l = t128 & 31;
  uint32_t b[18];
#pragma unroll
  for (int i = 0; i < 18; i++) b[i] = lds(red + 512 + (72 * w + 4 * i + (l & 3)) * 4);
  const uint32_t sa = pin(sw_ + (144 * w + (l & 7) + 8 * (l >> 4)) * 32 + (((l >> 3) ^ (l >> 2)) & 1) * 16);
  const uint32_t sr = pin(rb + (l >> 2) * 16 + w * 4);
  uint32_t* const dst = pin(mod_ptr(sc, u, t128));
  const int kind = u / 36;
  const float mul = __uint_as_float(pin(__float_as_uint(kind == 0 ? 16.0f : 1.0f))), add = __uint_as_float(pin(__float_as_uint(kind == 1 || kind == 4 ? 1.0f : 0.0f)));
  mbar_wait(bar, ph);
  if (t128 == 0 && u < 72) TS(10);
  float d[3][4];
#pragma unroll
  for (int i = 0; i < 9; i++) {
    uint32_t a0, a1, a2, a3;
    asm volatile("ldmatrix.sync.aligned.m8n8.x4.trans.shared.b16 {%0,%1,%2,%3}, [%4];" : "=r"(a0), "=r"(a1), "=r"(a2), "=r"(a3) : "r"(sa + i * 512) : "memory");
    if (i < 3) mma16<false>(d[i], a0, a1, a2, a3, b[2 * i], b[2 * i + 1]);
    else mma16<true>(d[i % 3], a0, a1, a2, a3, b[2 * i], b[2 * i + 1]);
  }
  if ((l & 3) == 0) { sts(sr, __float_as_uint(d[0][0] + d[1][0] + d[2][0])); sts(sr + 128, __float_as_uint(d[0][2] + d[1][2] + d[2][2])); }
  bar_sync(4, 128);
  const uint4 v = lds4(rb + (l & 15) * 16);
  const float m = rbf(fmaf(rbf((__uint_as_float(v.x) + __uint_as_float(v.y)) + (__uint_as_float(v.z) + __uint_as_float(v.w))), mul, add));
  if (u < 72 || t128 < 16) *dst = __float_as_uint(m) | tag;
}

__device__ __forceinline__ float rsq(float x) { float r; asm("rsqrt.approx.ftz.f32 %0, %1;" : "=f"(r) : "f"(x)); return r; }
__device__ __forceinline__ void ln_stats2(const float (&a)[18], const float (&b)[18], float sc, float& oa, float& ra, float& ob, float& rb) {
  float v[4] = {0.f, 0.f, 0.f, 0.f}, w[4] = {0.f, 0.f, 0.f, 0.f};
#pragma unroll
  for (int i = 0; i < 18; i += 2) {
    v[0] += a[i]; v[1] = fmaf(a[i], a[i], v[1]); v[2] += b[i]; v[3] = fmaf(b[i], b[i], v[3]);
    w[0] += a[i + 1]; w[1] = fmaf(a[i + 1], a[i + 1], w[1]); w[2] += b[i + 1]; w[3] = fmaf(b[i + 1], b[i + 1], w[3]);
  }
#pragma unroll
  for (int e = 0; e < 4; e++) v[e] += w[e];
#pragma unroll
  for (int o = 16; o; o >>= 1) {
#pragma unroll
    for (int e = 0; e < 4; e++) v[e] += __shfl_xor_sync(0xffffffffu, v[e], o);
  }
  const float ma = v[0] * (1.0f / D_), mb = v[2] * (1.0f / D_);
  ra = sc * rsq(fmaxf(fmaf(-ma, ma, v[1] * (1.0f / D_)), 0.f) + 1e-5f);
  rb = sc * rsq(fmaxf(fmaf(-mb, mb, v[3] * (1.0f / D_)), 0.f) + 1e-5f);
  oa = -ma * ra; ob = -mb * rb;
}

__device__ __forceinline__ float tmat(int c, int q, int j) {
  const int ph = q == 1 ? 1024 * j : (q >> 1) * (c + 128 * j) + 512 * (q & 1);
  return __cosf((float)(((ph + 1024) & 2047) - 1024) * (6.283185307179586f / 2048.0f));
}
__device__ __forceinline__ uint32_t line_off(int k1, int kap, int pi, int f) {
  int kd = 64 * k1 + 9 * kap;
  if (kap == 0 && k1 > 4) kd -= 288;
  if (kd >= D_) kd -= D_;
  return pi * 2400 + ((min(kd, D_ - kd) ^ f) << 3);
}

constexpr int JSK = 5;
struct Ring { uint32_t st, ph; };
template <bool G2, class T> __device__ __forceinline__ void ring_next(T& st, T& ph) {
  if (++st == NST) st = 0;
  ph ^= ((G2 ? 0xDu : 0x1u) >> st) & 1;
}
__device__ __forceinline__ void arrive_if(uint32_t a, uint32_t p) {
  asm volatile("{\n.reg .pred p;\nsetp.ne.u32 p, %1, 0;\n@p mbarrier.arrive.shared::cta.b64 _, [%0];\n}" ::"r"(a), "r"(p) : "memory");
}
template <int NA> __device__ __forceinline__ void reg_fence_n(float (&d)[96]) {
#pragma unroll
  for (int i = 0; i < NA; i++) asm volatile("" : "+f"(d[i])::"memory");
}
template <int MODE>
__device__ __forceinline__ void gemm_main(float (&acc)[96], uint32_t da0, uint32_t da1, uint32_t db0, int wg, Ring& rg,
                                          uint32_t* x1p, const uint32_t (&xr)[18]) {
  static_assert(JSK == NST - 1, "the held slot is the first one that is not refilled by GEMM1");
  constexpr int NKB = MODE == 3 ? 36 : 32;
  constexpr uint32_t HA = 0x40000040u, HB = MODE == 3 ? 0x40000040u : 0x80000020u;
  constexpr uint32_t KA = 2048 >> 4, KB = MODE == 3 ? (32 >> 4) : (1024 >> 4);
  constexpr int NA = MODE == 3 ? 72 : MODE == 1 ? 96 : 80;
  const uint32_t t = threadIdx.x & 127;
  const uint32_t eb = full0 + 8 * NST;
  uint32_t pb = 0, rel = t == 0, prel = 0, ok = 0;
  int n = MODE == 3 ? NKB - JSK : X1K + 2 * wg;
#pragma unroll 1
  for (int pass = MODE == 3 ? 0 : -1;; pass++) {
#pragma unroll 1
    do {
      const uint32_t so = rg.st * ((MODE == 3 ? STAGE2 : STAGE) >> 4), cb = eb + 8 * rg.st;
      if (__builtin_expect(!ok, 0)) mbar_wait(full0 + 8 * rg.st, rg.ph);
      reg_fence_n<NA>(acc);
      if (MODE == 1 && wg) {
        wg_fence();
#pragma unroll
        for (int k = 0; k < 4; k++) wgmma_ss<96, 48, 1>(acc, da1 + so + k * KA, HA, db0 + so + k * KB, HB);
        wg_commit();
      }
      wg_fence();
#pragma unroll
      for (int k = 0; k < 4; k++) {
        if (k == 3) { ring_next<MODE == 3>(rg.st, rg.ph); ok = PEEK ? mbar_test(full0 + 8 * rg.st, rg.ph) : 0; }
        if (MODE == 0) wgmma_ss<160, 0, 1>(acc, da0 + so + k * KA, HA, db0 + so + k * KB, HB);
        else if (MODE == 3) wgmma_ss<144, 0, 0>(acc, da0 + so + k * KA, HA, db0 + so + k * KB, HB);
        else wgmma_ss<96, 0, 1>(acc, da0 + so + k * KA, HA, db0 + so + k * KB, HB);
      }
      wg_commit();
      wg_wait<1>();
      reg_fence_n<NA>(acc);
      arrive_if(pb, prel);
      pb = cb; prel = rel;
    } while (--n);
    if (pass == 2 - wg) break;
    if (MODE != 3 && pass < 0) {
      if (blockIdx.x < 128) {
#pragma unroll
        for (int i = 0; i < 9; i++) { x1p[32 * i] = xr[i]; x1p[128 * 288 + 32 * i] = xr[9 + i]; }
      }
      n = NKB - JSK - X1K - 2 * wg;
      continue;
    }
    n = 1;
    if (pass == 0) {
      if (MODE != 3) prel = rel & wg;
      else rel = 0;
      n = JSK - 1 + wg;
      if (!wg) continue;
      wg_wait<0>();
      arrive_if(pb, prel);
      prel = 0;
    }
    bar_sync(1, 256);
  }
  wg_wait<0>();
  reg_fence_n<NA>(acc);
  if (MODE != 3) arrive_if(pb, MODE == 1 ? prel & ~wg : prel);
}

constexpr float GK1 = 2.0f * 0.7978845608028654f, GK3 = 8.0f * 0.044715f * 0.7978845608028654f;

__device__ __forceinline__ int kb2_order(int i) { const int wv = i / 6; return 6 * (i - 6 * wv) + ((0x431250 >> (4 * wv)) & 7); }

__device__ __forceinline__ void wait_flags(const unsigned* base, int n, int idx, unsigned target, uint64_t& ready) {
  if ((ready >> idx) & 1) return;
  const int l = threadIdx.x & 31;
  int it = 0;
  while (true) {
    unsigned a = ld_rlx(base + l), b = l + 32 < n ? ld_rlx(base + l + 32) : target;
    ready = (uint64_t)__ballot_sync(0xffffffffu, (int)(a - target) >= 0) | ((uint64_t)__ballot_sync(0xffffffffu, (int)(b - target) >= 0) << 32);
    if (((ready >> idx) & 1) || ++it > SPIN_MAX) break;
  }
}

enum { B_FULL = 0, B_EMPTY = 6, B_S4 = 12, B_S5, B_LAND, B_FLT = B_LAND + 6, B_Z1, B_Z2, B_GO, B_X, B_WM, B_NUM, B_W0 = B_NUM };

__global__ void __launch_bounds__(NTHR, 1)
fused_kernel(const Params p, const __grid_constant__ Maps maps) {
  extern __shared__ __align__(1024) uint8_t smem_raw[];
  const int tid = threadIdx.x, cta = blockIdx.x, t128 = tid & 127;
  const int wp = __shfl_sync(0xffffffffu, tid >> 5, 0), wg = wp >> 2;
  const int l = tid & 31, g = l >> 2, t = l & 3;
  Scratch* const sc = p.s;
  const bool rows = cta < 128;
  const int R = cta - 12;

  uint32_t xr[18];
  uint32_t cv[3];
  const unsigned ep = ld_rlx(&sc->cnt[C_EP]) + 1;
  if (tid == 0) TS(0);
  if (wg == 2) {
#pragma unroll
    for (int i = 0; i < 3; i++) cv[i] = ld_nc(reinterpret_cast<const uint32_t*>(p.c) + min(t128 + 128 * i, 287));
    if (wp == 9 && l < 9 && rows) {
      const int h = 9 * cta + l;
      prefetch_l2(reinterpret_cast<const uint8_t*>(p.wmod) + (size_t)(h >> 1) * (12 * D_) + (h & 1) * (2 * D_), 2 * D_);
    }
    if (tid == 256 && cta < 72) {
      mbar_init(full0 + 8 * B_W0, 1);
      fence_async_smem();
      mbar_expect(full0 + 8 * B_W0, 18432);
#pragma unroll 1
      for (int i = 0; i < 3; i++) tma2d(sbase + O_P2 + i * 6144, &maps.wm, 16 * cta, 192 * i, full0 + 8 * B_W0);
    }
    __syncwarp();
#pragma unroll 1
    for (int u = cta < 72 ? cta : 72 + cta; u < 216; u += u < 72 ? 72 : NCTA) if (u < 72 || t128 < 16) *mod_ptr(sc, u, t128) = 0;
    if (wp == 11 && smem_u32(smem_raw) != sbase) __trap();
    if (wp >= 10 && elect()) {
#pragma unroll 1
      for (int i = wp - 10; i < B_NUM; i += 2) mbar_init(full0 + 8 * i, i == B_FLT ? 4 : i == B_WM ? 3 : i < B_LAND ? 2 : 1);
      fence_async_smem();
    }
    __syncwarp();
  }
  CK(0);
  auto load_x = [&]() {
    const uint32_t* xs = reinterpret_cast<const uint32_t*>(p.x) + (size_t)(cta + 256 * wp) * 288 + l;
#pragma unroll
    for (int i = 0; i < 9; i++) { xr[i] = ld_nc(xs + 32 * i); xr[9 + i] = ld_nc(xs + 128 * 288 + 32 * i); }
  };
  if (rows && wg < 2) load_x();
  if (tid == 64 && cta == NCTA - 1) prefetch_l2(p.tab, sizeof(T_TAB));
  __syncwarp();
  const uint32_t tag16 = (ep & 0x7fffu) | 0x8000u, tag1 = ep & 1u;

  if (wg == 2) {
#pragma unroll
    for (int i = 0; i < 3; i++) {
      const float c0 = bf_lo(cv[i]), c1 = bf_hi(cv[i]);
      sts(red + 512 + min(t128 + 128 * i, 287) * 4, pack_bf16(__fdividef(c0, 1.0f + __expf(-c0)), __fdividef(c1, 1.0f + __expf(-c1))));
    }
    if (wp == 9 && l < 14) asm volatile("prefetch.tensormap [%0];" ::"l"(&maps.z1 + l) : "memory");
    bar_sync(4, 128);
    if (cta < 72) {
      mod_unit(sc, cta, t128, sbase + O_P2, full0 + 8 * B_W0, 0, red, tag16);
      if (t128 == 0) TS(25);
    }
    CK(1);
  }
  const int pi = R / 15, col0 = 20 * (R - 15 * pi);
  const int xu = DF_ * pi + col0, xv = DF_ * (pi ? 16 - pi : 8) + col0;
  auto load_filter = [&](int a) {
    const int x = (a & 1) ? xv : xu;
    const bool wide = (x & 15) > 12;
    mbar_expect(full0 + 8 * B_FLT, wide ? 12288 : 8192);
    tma2d(sbase + O_RAW + a * 12288, &maps.wf[a & 2], x & ~15, 0, full0 + 8 * B_FLT);
    if (wide) tma2d(sbase + O_RAW + a * 12288 + 8192, &maps.wf[(a & 2) + 1], (x & ~15) + 32, 0, full0 + 8 * B_FLT);
  };
  const int kap = 8 * ((wp & 3) ^ (wg & 1)) + g;
  uint4 af[4];
  if (rows) {
    uint32_t tb[4];
#pragma unroll
    for (int i = 0; i < 4; i++) tb[i] = pack_bf16(tmat(cta, 8 * (i >> 1) + g, 2 * t + 8 * (i & 1)), tmat(cta, 8 * (i >> 1) + g, 2 * t + 8 * (i & 1) + 1));
    uint32_t sb1[3], lo[9];
#pragma unroll
    for (int i = 0; i < 4; i++) tb[i] = pin(tb[i]);
#pragma unroll
    for (int i = 0; i < 3; i++) {
      const int d = 48 * wp + 16 * i + (l & 15);
      sb1[i] = pin(sbase + O_B1 + (l >> 4) * 9216 + (d % 9) * 1024 + (d & 63) * 16);
    }
    const uint32_t snt = pin(sbase + O_NRM + ((l & 7) + 8 * (l >> 4)) * 1168 + (48 * wp + (l & 8)) * 2);
    uint2 ms[3], mc[3];
    const uint32_t smask = pin(t ? 0u : 0xffff0000u);
    const uint32_t* const mp = pin(sc->moda + (cta >> 4) * (2 * D_) + 48 * wp + 2 * g);
    auto load_mod = [&]() {
#pragma unroll
      for (int i = 0; i < 3; i++) { ms[i] = ld_rlx2(mp + 16 * i); mc[i] = ld_rlx2(mp + D_ + 16 * i); }
    };
    if (wg < 2) {
#pragma unroll
      for (int k1 = 0; k1 < 9; k1++) lo[k1] = pin(sbase + O_Z1 + line_off(k1, kap, 4 * wg + t, cta & 3));
      float a[18], b[18];
#pragma unroll
      for (int i = 0; i < 9; i++) { a[2 * i] = bf_lo(xr[i]); a[2 * i + 1] = bf_hi(xr[i]); b[2 * i] = bf_lo(xr[9 + i]); b[2 * i + 1] = bf_hi(xr[9 + i]); }
      float oa, ra, ob, rb;
      ln_stats2(a, b, 1.0f, oa, ra, ob, rb);
      CK(1);
      const uint32_t sn = sbase + O_NRM + wp * 2336 + l * 4;
#pragma unroll
      for (int i = 0; i < 9; i++) {
        sts(sn + i * 128, pack_bf16(fmaf(a[2 * i], ra, oa), fmaf(a[2 * i + 1], ra, oa)));
        sts(sn + 1168 + i * 128, pack_bf16(fmaf(b[2 * i], rb, ob), fmaf(b[2 * i + 1], rb, ob)));
      }
      CK(2);
      bar_arrive(10, NTHR);
      load_mod();
#pragma unroll
      for (int kk = 0; kk < 4; kk++) af[kk] = ld_nc4(p.tab + TB_F + kk * 128 + (t128 ^ (wg << 5)));
      bar_sync(1, 256);
      if (tid == 0) TS(2);
    } else {
      bar_sync(10, NTHR);
      load_mod();
      CK(2);
      if (PFF && wp >= 12 - PFF && elect()) prefetch_l2(reinterpret_cast<const uint8_t*>(wp == 10 ? p.wr : p.wi) + cta * 9248, 9248);
      __syncwarp();
    }
    float rs[3][8];
#pragma unroll
    for (int i = 0; i < 3; i++) {
      uint32_t a0, a1, a2, a3;
      asm volatile("ldmatrix.sync.aligned.m8n8.x4.trans.shared.b16 {%0,%1,%2,%3}, [%4];" : "=r"(a0), "=r"(a1), "=r"(a2), "=r"(a3)
                   : "r"(snt + 32 * i) : "memory");
      mma16<false>(&rs[i][0], a0, a1, a2, a3, tb[0], tb[1]);
      mma16<false>(&rs[i][4], a0, a1, a2, a3, tb[2], tb[3]);
    }
    CK(3);
    {
      int it = 0;
#pragma unroll 1
      while (true) {
        uint32_t bad = 0;
#pragma unroll
        for (int i = 0; i < 3; i++) bad |= diff2(ms[i].x, ms[i].y, tag16) | diff2(mc[i].x, mc[i].y, tag16);
        if (!any(bad & 0xffffu) || ++it > SPIN_MAX) break;
        load_mod();
      }
      CK(4);
      if (tid == 0) TS(3);
#pragma unroll
      for (int i = 0; i < 3; i++) {
        const float c0 = bf_hi(mc[i].x), c1 = bf_hi(mc[i].y);
        const float s0 = __uint_as_float(ms[i].x & smask), s1 = __uint_as_float(ms[i].y & smask);
        stmatrix4(sb1[i], pack_bf16(fmaf(rs[i][0], c0, s0), rs[i][1] * c0), pack_bf16(fmaf(rs[i][2], c1, s1), rs[i][3] * c1),
                  pack_bf16(rs[i][4] * c0, rs[i][5] * c0), pack_bf16(rs[i][6] * c1, rs[i][7] * c1));
      }
    }
    fence_async_smem();
    CK(5);
    if (wg == 2) {
      bar_arrive(5, NTHR);
      if (R >= 0 && elect()) load_filter(wp - 8);
      __syncwarp();
    } else {
      bar_sync(5, NTHR);
      CK(6);
      float acc[36];
      const uint32_t db = (((sbase + O_B1 + wg * 9216) & 0x3FFFF) >> 4) | ((128 >> 4) << 16);
      wg_fence();
#pragma unroll
      for (int kk = 0; kk < 4; kk++) wgmma_rs_72(acc, af[kk].x, af[kk].y, af[kk].z, af[kk].w, db + kk * 16, 1024 >> 4, kk);
      wg_commit();
      wg_wait<0>();
      reg_fence(acc);
      CK(7);
      float2 za[9], zb[9];
#pragma unroll
      for (int i = 0; i < 9; i++) { za[i] = make_float2(acc[4 * i], acc[4 * i + 2]); zb[i] = make_float2(acc[4 * i + 1], acc[4 * i + 3]); }
      dft9(za); dft9(zb);
      if (kap == 0) {
#pragma unroll
        for (int k = 1; k < 5; k++) {
          float2 a = za[k], b = za[9 - k];
          za[k] = make_float2(a.x + b.x, a.y - b.y); za[9 - k] = make_float2(a.y + b.y, b.x - a.x);
          a = zb[k]; b = zb[9 - k];
          zb[k] = make_float2(a.x + b.x, a.y - b.y); zb[9 - k] = make_float2(a.y + b.y, b.x - a.x);
        }
        sts2(lo[0] + 288 * 8, set_tag(pack_bf16(za[0].y, 0.f), tag1), pack_bf16(zb[0].y, 0.f));
        za[0].y = 0.f; zb[0].y = 0.f;
      }
      __syncwarp();
#pragma unroll
      for (int k1 = 0; k1 < 9; k1++) sts2(lo[k1], set_tag(pack_bf16(za[k1].x, za[k1].y), tag1), pack_bf16(zb[k1].x, zb[k1].y));
      fence_async_smem();
      CK(8);
      bar_arrive(2 + wg, 160);
      {
        const uint32_t fx = (((cta >> 4) ^ cta) & 3) << 3, dl = O_IN - O_Z1, st = sbase + O_ST + 15360 + tid * 16;
        sts4(st, (lo[0] ^ fx) + dl, (lo[1] ^ fx) + dl, (lo[2] ^ fx) + dl, (lo[3] ^ fx) + dl);
        sts4(st + 4096, (lo[4] ^ fx) + dl, (lo[5] ^ fx) + dl, (lo[6] ^ fx) + dl, (lo[7] ^ fx) + dl);
        sts4(st + 8192, (lo[8] ^ fx) + dl, (lo[0] ^ fx) + dl + (kap ? 0 : 288 * 8),
             sbase + O_B3 + wg * 1024 + (l >> 4) * 2048 + (2 * (kap & 24) + (l & 15)) * 16, 0);
      }
    }
    {
      uint32_t sy[6];
#pragma unroll
      for (int i = 0; i < 6; i++) {
        const int rr = 16 * (wp & 3) + g + 8 * (i & 1);
        sy[i] = sbase + O_Y + (t * 584 + 64 * ((3 * wg + (i >> 1) + 63 - rr) % 9) + rr) * 4;
      }
      sts4(sbase + O_ST + tid * 16, movm(tb[0]), movm(tb[2]), movm(tb[1]), movm(tb[3]));
      sts4(sbase + O_ST + 6144 + tid * 16, sy[0], sy[1], sy[2], sy[3]);
      sts2(sbase + O_ST + 12288 + tid * 8, sy[4], sy[5]);
    }
  } else {
    __syncthreads();
  }

  if ((wp >> 1) == 4) {
    if (rows) {
      const int slot = 4 * (cta & 7) + ((cta >> 4) & 3) + 32 * (2 * (cta >> 6) + ((cta >> 3) & 1));
      const uint32_t c0 = upin(40 * slot), c1 = upin(60 * (wp - 8)), src = upin(sbase + O_Z1 + (wp - 8) * 9600);
      const CUtensorMap* mp = upin(&maps.z1);
      unsigned* hint = pin(&sc->cnt[C_Z1 + 32 * (wp - 8)]);
      bar_sync(wp - 6, 160);
      if (elect()) {
        tma_st2d(mp, src, c0, c1);
        HW();
        red_add(hint, 1);
        if (wp == 8) TS(4);
      }
    } else {
      int it = 0;
      while (any((ld_rlx(sc->moda + 36 * l) ^ tag16) & 0xffffu) && ++it < SPIN_MAX) {}
      if (elect()) { load_filter(wp - 8); load_filter(wp - 6); }
    }
    __syncwarp();
  }
  auto load_wm = [&](int u) {
    if (wp > 8 && elect()) {
      mbar_expect(full0 + 8 * B_WM, 6144);
      tma2d(sbase + O_NRM + (wp - 9) * 6144, &maps.wm, 16 * u, 192 * (wp - 9), full0 + 8 * B_WM);
    }
    __syncwarp();
  };
  if (R >= 0) {
    const int nl = (col0 + wp < DF_) + (wg < 2 && col0 + wp + 12 < DF_);
    uint4 cf[2][4], G[4];
#pragma unroll
    for (int i = 0; i < 4; i++) {
      cf[0][i] = __ldg(p.tab + TB_P2 + i * 32 + l);
      cf[1][i] = __ldg(p.tab + TB_P2 + (pi ? i : 4 + i) * 32 + l);
      G[i] = __ldg(p.tab + TB_P2 + (8 + i) * 32 + l);
    }
    const uint32_t* zin = sc->z1 + (size_t)R * 5120;
    if (wp == 10) {
      const uint32_t* zu = upin(zin);
      if (elect()) mbar_expect(full0 + 8 * B_Z1, 20480);
      wait_cnt(&sc->cnt[C_Z1 + 32 * (pi >> 2)], 128 * ep);
      if (elect()) {
        bulk_ld(sbase + O_P2, zu, 20480, full0 + 8 * B_Z1);
        TS(12);
      }
      __syncwarp();
    }
    mbar_wait(full0 + 8 * B_FLT, 0);
    CK(9);
    float wn[16], wc[16];
#pragma unroll 1
    for (int ln = nl - 1; ln >= 0; ln--) {
      const int col = col0 + wp + 12 * ln, k2 = (57 * col) & 63;
      const bool cj = k2 > 32 || (k2 == 32 && col != 288);
      const float nr = ((col & 31) == 0 && col != 0 && col != 288 ? 0.5f : 1.0f) / ((float)S_ * D_), ni = cj ? -nr : nr;
#pragma unroll
      for (int i = 0; i < 16; i++) wn[i] = wc[i];
#pragma unroll
      for (int cl = 0; cl < 2; cl++) {
        const int v = cl ^ (cj && pi), e = ((v ? xv : xu) & 15) + wp + 12 * ln, sh = e < 32 ? 6 : 5;
        const uint32_t base = sbase + O_RAW + v * 12288 + (e < 32 ? 2 * e : 8192 - 64 + 2 * e), msk = e < 32 ? 0x30 : 0x10;
        const int dm = v ? (cj || pi ? -1 : 0) : 0;
#pragma unroll
        for (int tt = 0; tt < 4; tt++) {
          const int kc = g + 64 * (tt >> 1) + 16 * t + 8 * (tt & 1);
          uint32_t a = base + ((((cj ? -kc : kc) + dm) & 127) << sh);
          a ^= (a >> 3) & msk;
          wc[4 * tt + 2 * cl] = lds_bf(a) * nr; wc[4 * tt + 2 * cl + 1] = lds_bf(a + 24576) * ni;
        }
      }
    }
    const float al = __uint_as_float(pin((pi ? 0x3f800000u : 0u) + (l >> 5)));
    const uint32_t tagv = pin(tag1 + (l >> 5));
    CK(10);
    uint32_t off = pin(l * 160 + ((wp ^ (g & 3)) << 3));
    uint32_t offo = pin(sbase + O_P2 + 20480 + off - 64 * l), po = 3072;
    unsigned* hz2 = pin(&sc->cnt[C_Z2]);
    const uint32_t do2 = pin(12288 - 32 * l);
    const CUtensorMap* mz2 = upin(&maps.z2[wp == 0]);
    const uint32_t sz2 = upin(sbase + O_P2 + 20480 + (wp ? 0 : 12288)), cz2 = upin(40 * R + (wp ? 0 : 24));
    mbar_wait(full0 + 8 * B_Z1, 0);
    CK(11);
    if (tid == 0) TS(8);
    if (wg == 2) load_wm(72 + cta);
    uint2 v[4], v2[4];
    const uint32_t o2 = nl > 1 ? 96 : 0;
#pragma unroll
    for (int i = 0; i < 4; i++) { v[i] = lds2(sbase + O_P2 + off + i * 5120); v2[i] = lds2(sbase + O_P2 + off + o2 + i * 5120); }
    auto bad2 = [&]() {
      return any(or3(or3(diff2(v[0].x, v[1].x, tagv), diff2(v[2].x, v[3].x, tagv), diff2(v2[0].x, v2[1].x, tagv)), diff2(v2[2].x, v2[3].x, tagv), 0) & 1);
    };
    if (__builtin_expect(bad2() && nl, 0)) {
      FAILCNT(0);
      int it = 0;
      do {
#pragma unroll
        for (int i = 0; i < 4; i++) {
          v[i] = ld_rlx2(reinterpret_cast<const uint8_t*>(zin) + off + i * 5120);
          v2[i] = ld_rlx2(reinterpret_cast<const uint8_t*>(zin) + off + o2 + i * 5120);
        }
      } while (bad2() && ++it < SPIN_MAX);
    }
#pragma unroll 1
    for (int ln = 0; ln < nl; ln++, offo += do2, po = 2048) {
      float d[4][4];
      uint32_t A[8];
#pragma unroll
      for (int h = 0; h < 2; h++) {
        mma16<false>(d[2 * h], cf[0][0].x, cf[0][0].y, cf[0][0].z, cf[0][0].w, v[h].x, v[2 + h].x);
        mma16<false>(d[2 * h + 1], cf[1][0].x, cf[1][0].y, cf[1][0].z, cf[1][0].w, v[h].y, v[2 + h].y);
      }
      if (ln) { fence_async_smem(); bar_arrive(15, NTHR); }
#pragma unroll
      for (int h = 0; h < 2; h++)
#pragma unroll
        for (int L = 0; L < 2; L++) {
          const uint4 tw = cf[L][2 + h];
          const float* z = d[2 * h + L];
          const float2 z0 = cmul(make_float2(z[0], z[2]), make_float2(__uint_as_float(tw.x), __uint_as_float(tw.y)));
          const float2 z1 = cmul(make_float2(z[1], z[3]), make_float2(__uint_as_float(tw.z), __uint_as_float(tw.w)));
          A[4 * h + L] = pack_bf16(z0.x, z0.y); A[4 * h + 2 + L] = pack_bf16(z1.x, z1.y);
        }
#pragma unroll
      for (int tt = 0; tt < 4; tt++) {
        mma16<false>(d[tt], A[0], A[1], A[2], A[3], G[tt].x, G[tt].y);
        mma16<true>(d[tt], A[4], A[5], A[6], A[7], G[tt].z, G[tt].w);
      }
#pragma unroll
      for (int tt = 0; tt < 4; tt++) {
        const float ar = d[tt][0], aj = d[tt][1], br = d[tt][2], bj = d[tt][3];
        const float2 y1 = cmul(make_float2(fmaf(-al, bj, ar), fmaf(al, br, aj)), make_float2(wc[4 * tt], wc[4 * tt + 1]));
        const float2 y2 = cmul(make_float2(fmaf(al, ar, bj), fmaf(al, aj, -br)), make_float2(wc[4 * tt + 2], wc[4 * tt + 3]));
        A[2 * tt] = pack_bf16(fmaf(al, y2.x, y1.x), fmaf(-al, y2.y, -y1.y));
        A[2 * tt + 1] = pack_bf16(fmaf(al, y1.y, -y2.y), fmaf(al, y1.x, -y2.x));
      }
#pragma unroll
      for (int i = 0; i < 16; i++) wc[i] = wn[i];
#pragma unroll
      for (int i = 0; i < 4; i++) v[i] = v2[i];
#pragma unroll
      for (int tt = 0; tt < 4; tt++) {
        mma16<false>(d[tt], A[0], A[1], A[2], A[3], G[tt].x, G[tt].y);
        mma16<true>(d[tt], A[4], A[5], A[6], A[7], G[tt].z, G[tt].w);
      }
#pragma unroll
      for (int h = 0; h < 2; h++)
#pragma unroll
        for (int L = 0; L < 2; L++) {
          const uint4 tw = cf[L][2 + h];
          const float2 z0 = cmul(make_float2(d[2 * h][2 * L], d[2 * h][2 * L + 1]), make_float2(__uint_as_float(tw.x), __uint_as_float(tw.y)));
          const float2 z1 = cmul(make_float2(d[2 * h + 1][2 * L], d[2 * h + 1][2 * L + 1]), make_float2(__uint_as_float(tw.z), __uint_as_float(tw.w)));
          A[4 * h + 2 * L] = movm(pack_bf16(z0.x, z1.x)); A[4 * h + 2 * L + 1] = movm(pack_bf16(z0.y, z1.y));
        }
#pragma unroll
      for (int h = 0; h < 2; h++) {
        mma16<false>(d[0], cf[0][1].x, cf[0][1].y, cf[0][1].z, cf[0][1].w, A[4 * h], A[4 * h + 1]);
        mma16<false>(d[1], cf[1][1].x, cf[1][1].y, cf[1][1].z, cf[1][1].w, A[4 * h + 2], A[4 * h + 3]);
#pragma unroll
        for (int e = 0; e < 2; e++)
          sts2(offo + (2 * h + e) * po, set_tag(pack_bf16(d[0][e], d[0][2 + e]), tagv), pack_bf16(d[1][e], d[1][2 + e]));
      }
      CK(12 + ln);
    }
    fence_async_smem();
    if (nl < 2 && wp != 8) bar_arrive(15, NTHR);
    if (wp & 7) { if (wg < 2) bar_arrive(6, 256); }
    else {
      if (wp) bar_sync(15, NTHR); else bar_sync(6, 256);
      if (elect()) {
        tma_st2d(mz2, sz2, cz2, 0);
        HW();
        if (wp == 0) { red_add(hz2, 1); TS(9); }
      }
      __syncwarp();
    }
  }
  if (wg == 2) {
#pragma unroll 1
    for (int u = 72 + cta, k = 0; u < 216; u += NCTA, k ^= 1) {
      if (R < 0) { fence_async_smem(); bar_sync(4, 128); load_wm(u); }
      mod_unit(sc, u, t128, sbase + O_NRM, full0 + 8 * B_WM, k, red + 256 - 256 * k, tag16);
    }
    fence_async_smem();
    CK(13);
  }

  const int grp = cta / 11, m1 = cta - 11 * grp;
  const bool helper = (m1 & 3) == 3;
  const int f1 = 384 * grp + (helper ? 192 : 128) * (m1 >> 2);
  const int d1 = 160 * (m1 & 3), flip = m1 >= 7;
  const int a1bytes = helper ? 24576 : 16384;
  auto load_a1 = [&](int st, int kb) {
    mbar_expect(full0 + 8 * st, a1bytes);
    tma4d_ef(sbase + st * STAGE, helper ? &maps.w1b : &maps.w1a, 4 * (kb >> 3), 16 * (kb & 7), f1 >> 6, full0 + 8 * st);
  };

  if (rows) {
#pragma unroll
    for (int kk = 0; kk < 4; kk++) af[kk] = __ldg(p.tab + TB_E + kk * 128 + t128);
    const uint4 c0 = lds4(sbase + O_ST + tid * 16), c1 = lds4(sbase + O_ST + 6144 + tid * 16);
    const uint2 c2 = lds2(sbase + O_ST + 12288 + tid * 8);
    const uint32_t tb[4] = {c0.x, c0.y, c0.z, c0.w}, sy[6] = {c1.x, c1.y, c1.z, c1.w, c2.x, c2.y};
    const uint32_t l8 = pin(8 * l), syl = pin(sbase + O_Y + wp * 2336 + 8 * l);
    const uint32_t sh3 = pin(sbase + O_B3 + (wp >> 1) * 4608 + (l >> 4) * 256 + (wp & 1) * 128 + ((((l >> 2) ^ (2 * cta + (wp & 1))) & 3) << 4) + (l & 3) * 4);
    const bool htag = (((sh3 >> 2) ^ (2 * cta + (wp & 1))) & 7) == 0;
    const uint32_t ham = pin(htag ? ~1u : ~0u), hom = pin(htag ? tag1 : 0u);
    const int slot = 4 * (cta >> 4) + ((cta >> 1) & 3) + 32 * (2 * ((cta >> 3) & 1) + (cta & 1));
    const uint32_t* zin = sc->z2 + (size_t)slot * 4800;
    if (wg == 2) {
      {
        uint4 v[4];
        const int i3 = min(t128 + 384, 431);
        int it = 0;
        while (true) {
          uint32_t bad = 0;
#pragma unroll
          for (int k = 0; k < 4; k++) v[k] = ld_rlx4(sc->mod + 4 * (k < 3 ? t128 + 128 * k : i3));
#pragma unroll
          for (int k = 0; k < 4; k++) {
            v[k].x ^= tag16; v[k].y ^= tag16; v[k].z ^= tag16; v[k].w ^= tag16;
            bad |= v[k].x | v[k].y | v[k].z | v[k].w;
          }
          if (!any(bad & 0xffffu) || ++it > SPIN_MAX) break;
        }
#pragma unroll
        for (int k = 0; k < 4; k++) sts4(sbase + O_MOD + 16 * (k < 3 ? t128 + 128 * k : i3), v[k].x, v[k].y, v[k].z, v[k].w);
      }
      CK(14);
      bar_sync(10, NTHR);
      mbar_wait(full0 + 8 * B_Z2, 0);
      if (elect()) {
        load_a1(wp - 8, wp - 8);
        if (wp > 8 && wp - 8 < NG1) prefetch_l2(reinterpret_cast<const uint8_t*>(p.w1) + (size_t)(128 * (4 * ((wp - 8) >> 1) + (cta >> 5)) + 64 * (wp & 1) + 2 * (cta & 31)) * (2 * F_), 4 * F_);
      }
      __syncwarp();
    } else {
      const uint4 e0 = lds4(sbase + O_ST + 15360 + tid * 16), e1 = lds4(sbase + O_ST + 19456 + tid * 16), e2 = lds4(sbase + O_ST + 23552 + tid * 16);
      const uint32_t lo[9] = {e0.x, e0.y, e0.z, e0.w, e1.x, e1.y, e1.z, e1.w, e2.x}, lx = e2.y, sb3 = e2.z;
      bar_arrive(10, NTHR);
      CK(14);
      if (wp == 1) {
        const uint32_t* zu = upin(zin);
        if (elect()) mbar_expect(full0 + 8 * B_Z2, 19200);
        wait_cnt(&sc->cnt[C_Z2], 120 * ep);
        if (elect()) {
          bulk_ld(sbase + O_IN, zu, 19200, full0 + 8 * B_Z2);
          TS(14);
        }
        __syncwarp();
      }
      mbar_wait(full0 + 8 * B_Z2, 0);
      CK(15);
      if (tid == 0) TS(11);
      uint2 v[10];
#pragma unroll
      for (int k1 = 0; k1 < 10; k1++) v[k1] = lds2(k1 < 9 ? lo[k1] : lx);
      auto bad3 = [&]() {
        return any(or3(or3(diff2(v[0].x, v[1].x, tag1), diff2(v[2].x, v[3].x, tag1), diff2(v[4].x, v[5].x, tag1)), diff2(v[6].x, v[7].x, tag1), diff2(v[8].x, v[9].x, tag1)) & 1);
      };
      if (__builtin_expect(bad3(), 0)) {
        FAILCNT(1);
        int it = 0;
        do {
#pragma unroll
          for (int k1 = 0; k1 < 10; k1++) v[k1] = ld_rlx2(reinterpret_cast<const uint8_t*>(zin) + ((k1 < 9 ? lo[k1] : lx) - (sbase + O_IN)));
        } while (bad3() && ++it < SPIN_MAX);
      }
      float2 za[9], zb[9];
#pragma unroll
      for (int i = 0; i < 9; i++) { za[i] = make_float2(bf_lo(v[i].x), bf_hi(v[i].x)); zb[i] = make_float2(bf_lo(v[i].y), bf_hi(v[i].y)); }
      if (kap == 0) {
#pragma unroll
        for (int k = 1; k < 5; k++) {
          float2 a = za[k], b = za[9 - k];
          za[k] = make_float2(a.x - b.y, a.y + b.x); za[9 - k] = make_float2(a.x + b.y, b.x - a.y);
          a = zb[k]; b = zb[9 - k];
          zb[k] = make_float2(a.x - b.y, a.y + b.x); zb[9 - k] = make_float2(a.x + b.y, b.x - a.y);
        }
        za[0].y = bf_lo(v[9].x); zb[0].y = bf_lo(v[9].y);
      }
      __syncwarp();
      dft9(za); dft9(zb);
#pragma unroll
      for (int n = 0; n < 8; n += 2) {
        const int i0 = (9 - n) % 9, i1 = 8 - n;
        stmatrix4(sb3 + n * 2048, pack_bf16(za[i0].x, zb[i0].x), pack_bf16(za[i0].y, zb[i0].y), pack_bf16(za[i1].x, zb[i1].x), pack_bf16(za[i1].y, zb[i1].y));
      }
      stmatrix2(sb3 + 8 * 2048, pack_bf16(za[1].x, zb[1].x), pack_bf16(za[1].y, zb[1].y));
      fence_async_smem();
    }
    CK(16);
    __syncthreads();
    CK(17);
    float acc[24];
    const uint32_t db = (((sbase + O_B3 + wg * 6144) & 0x3FFFF) >> 4) | ((128 >> 4) << 16);
    wg_fence();
#pragma unroll
    for (int kk = 0; kk < 4; kk++) wgmma_rs_48(acc, af[kk].x, af[kk].y, af[kk].z, af[kk].w, db + kk * 16, 1024 >> 4, kk);
    wg_commit();
    uint32_t ga[9];
    uint2 sh[9], sw[9];
    if (wg < 2) {
#pragma unroll
      for (int i = 0; i < 9; i++) {
        const uint2 v = lds2(l8 + sbase + O_MOD + 256 * i);
        ga[i] = __byte_perm(v.x, v.y, 0x7632);
        sh[i] = lds2(l8 + sbase + O_MOD + 4 * D_ + 256 * i);
        sw[i] = lds2(l8 + sbase + O_MOD + 8 * D_ + 256 * i);
      }
    }
    wg_wait<0>();
    reg_fence(acc);
    CK(18);
#pragma unroll
    for (int i = 0; i < 3; i++) {
      const float* a = &acc[8 * i];
      const uint32_t a0 = pack_bf16(a[0], a[1]), a1 = pack_bf16(a[2], a[3]), a2 = pack_bf16(a[4], a[5]), a3 = pack_bf16(a[6], a[7]);
#pragma unroll
      for (int jh = 0; jh < 2; jh++) {
        float y[4];
        mma16<false>(y, a0, a1, a2, a3, tb[2 * jh], tb[2 * jh + 1]);
        sts(sy[2 * i] + jh * (4 * 584 * 4), pack_bf16(y[0], y[1]));
        sts(sy[2 * i + 1] + jh * (4 * 584 * 4), pack_bf16(y[2], y[3]));
      }
    }
    CK(19);
    if (wg == 2) bar_arrive(7, NTHR);
    else {
      bar_sync(7, NTHR);
      CK(20);
      float a[18], b[18];
#pragma unroll
      for (int i = 0; i < 9; i++) {
        const uint2 y = lds2(syl + 256 * i);
        xr[i] = hfma2(ga[i], __byte_perm(y.x, y.y, 0x5410), xr[i]);
        xr[9 + i] = hfma2(ga[i], __byte_perm(y.x, y.y, 0x7632), xr[9 + i]);
        a[2 * i] = bf_lo(xr[i]); a[2 * i + 1] = bf_hi(xr[i]); b[2 * i] = bf_lo(xr[9 + i]); b[2 * i + 1] = bf_hi(xr[9 + i]);
      }
      float oa, ra, ob, rb;
      ln_stats2(a, b, 1.0f, oa, ra, ob, rb);
      CK(21);
#pragma unroll
      for (int i = 0; i < 9; i++) {
        const float c0 = __uint_as_float(sw[i].x), c1 = __uint_as_float(sw[i].y), s0 = __uint_as_float(sh[i].x), s1 = __uint_as_float(sh[i].y);
        a[2 * i] = fmaf(fmaf(a[2 * i], ra, oa), c0, s0); a[2 * i + 1] = fmaf(fmaf(a[2 * i + 1], ra, oa), c1, s1);
        b[2 * i] = fmaf(fmaf(b[2 * i], rb, ob), c0, s0); b[2 * i + 1] = fmaf(fmaf(b[2 * i + 1], rb, ob), c1, s1);
      }
      ln_stats2(a, b, 0.5f, oa, ra, ob, rb);
      CK(22);
#pragma unroll
      for (int i = 0; i < 9; i++) {
        sts(sh3 + i * 512, and_or(pack_bf16(fmaf(a[2 * i], ra, oa), fmaf(a[2 * i + 1], ra, oa)), ham, hom));
        sts(sh3 + i * 512 + 64, and_or(pack_bf16(fmaf(b[2 * i], rb, ob), fmaf(b[2 * i + 1], rb, ob)), ham, hom));
      }
      fence_async_smem();
      if (wp == 0) CKX(0);
      if (wp < 2 * H3G) bar_arrive(8, 32 + 64 * H3G); else bar_arrive(9, 288 - 64 * H3G);
      CK(23);
    }
  } else __syncthreads();

  const bool g2 = cta < 130 && (cta >> 1) != 56;
  const int z2 = cta < 112 ? cta : cta - 2, r = z2 >> 6;
  const int s2 = 128 * ((z2 >> 2) & 15), d2 = 144 * (z2 & 3);
  constexpr int XST = (33 + 36 - JSK - 1) % NST;
  constexpr int ST0 = (32 - JSK - 1) % NST, ST1 = 31 % NST;

  if (wg == 2) {
    asm volatile("setmaxnreg.dec.sync.aligned.u32 40;");
    auto load_b = [&](bool second, int i, int st) {
      const uint32_t lb = full0 + 8 * (B_LAND + st), bytes = second ? 18432 : STAGE - a1bytes;
      mbar_expect(lb, bytes);
      bulk_ld(sbase + (second ? st * STAGE2 + 16384 : st * STAGE + a1bytes),
              second ? sc->u + ((size_t)(36 * r + kb2_order(i)) * D_ + d2) * 128 : sc->h3 + ((size_t)(i * 18 + (d1 >> 5)) << 12), bytes, lb);
    };
    if (wp == 8) {
      int st = rows ? 4 : 0, ph = 1;
#pragma unroll 1
      for (int kb = st; kb < 32; kb++) {
        if (rows && (kb >> 1) == 2) mbar_wait(full0 + 8 * (B_S4 - 4 + kb), 0);
        mbar_wait(empty0 + 8 * st, ph);
        if (elect()) {
          load_a1(st, kb);
          if (kb >= PF2K && kb < PF2K + PF2 && g2)
            prefetch_l2(reinterpret_cast<const uint8_t*>(p.w2) + (size_t)(36 * r + kb2_order(kb - PF2K)) * 262144 + (z2 & 63) * 4096, 4096);
        }
        __syncwarp();
        ring_next<false>(st, ph);
      }
      if (g2) {
        st++;
#pragma unroll 1
        for (int i = 0; i < 36; i++) {
          if (i == HOLDA) mbar_wait(full0 + 8 * B_GO, 0);
          mbar_wait(empty0 + 8 * st, ph);
          if (elect()) {
            mbar_expect(full0 + 8 * st, 16384);
            tma3d_ef(sbase + st * STAGE2, &maps.w2, 64 * (36 * r + kb2_order(i)), s2 >> 6, full0 + 8 * st);
          }
          __syncwarp();
          ring_next<true>(st, ph);
        }
      }
    } else if (wp >= 10) {
      const int sw = wp - 10;
      if (rows) {
        const CUtensorMap* mp = upin(&maps.h3[sw]);
        const uint32_t src = upin(sbase + O_B3 + sw * (H3G * 4608)), c0 = upin(64 * (cta & 15)), c1 = upin(18 * (cta >> 4)), c2 = upin(H3G * sw);
        unsigned* flag = pin(&sc->cnt[C_H3 + (cta >> 4) + 8 * sw]);
        bar_sync(8 + sw, sw ? 288 - 64 * H3G : 32 + 64 * H3G);
        if (!sw) CKX(1);
        if (sw) { mbar_wait(full0 + 8 * H3W, 0); CKX(7); }
        if (elect()) {
          tma_st3d(mp, src, c0, c1, c2);
          if (!sw) CKX(2);
          mbar_arrive(full0 + 8 * B_S4);
          bulk_commit_wait();
          if (!sw) CKX(3);
          red_add(flag, 1);
          mbar_arrive(full0 + 8 * B_S5);
          if (!sw) CKX(4);
          TS(sw ? 24 : 13);
        }
        __syncwarp();
      }
      if (sw) {
        if (rows) {
          mbar_wait(full0 + 8 * B_S5, 0);
          if (elect()) { asm volatile("fence.acq_rel.gpu;" ::: "memory"); red_add(&sc->cnt[C_X + 64], 1); }
          __syncwarp();
        }
        wait_cnt(&sc->cnt[C_X + 64], 128 * ep);
        if (elect()) mbar_arrive(full0 + 8 * B_X);
        __syncwarp();
      }
      if (sw && g2) {
#pragma unroll 1
        for (int i = 0; i < 36; i++) { sc->part[z2 * 1152 + 32 * i + l] = make_uint4(tag1 ^ 1, 0, 0, 0); __nanosleep(100); }
        __syncwarp();
      }
      uint32_t lph = 0;
      auto check_tiles = [&](bool second, int n, int st, uint32_t o1, uint32_t d2nd) {
        const uint32_t b1 = pin(sbase + o1), b2 = pin(sbase + o1 + d2nd);
        int i = 0, it = 0;
#pragma unroll 1
        do {
          const uint32_t so = st * (second ? STAGE2 : STAGE);
          mbar_wait(full0 + 8 * (B_LAND + st), (lph >> st) & 1);
          lph ^= 1u << st;
          uint32_t v[20];
#pragma unroll
          for (int k = 0; k < 20; k++) if (!second || k < 10 || k >= 12) v[k] = lds(k < 12 ? b1 + so + k * 1024 : b2 + so + (k - 12) * 1024); else v[k] = tag1;
#pragma unroll
          for (int k = 0; k < 10; k++) v[k] = diff2(v[2 * k], v[2 * k + 1], tag1);
          const uint32_t bad = or3(or3(or3(v[0], v[1], v[2]), or3(v[3], v[4], v[5]), v[6]), v[7], or3(v[8], v[9], 0));
          if (__builtin_expect(any(bad & 1) && ++it < SPIN_MAX, 0)) {
            FAILCNT(2 + second);
            fence_async_smem();
            __syncwarp();
            if (elect()) load_b(second, i, st);
            __syncwarp();
            continue;
          }
          if (elect()) mbar_arrive(full0 + 8 * st);
          if (second && i < 6) CKX(12 + 3 * i);
          if (++st == NST) st = 0;
          i++;
        } while (i < n);
      };
      if (!sw) check_tiles(false, NV1, 0, a1bytes + l * 32 + (l >> 2) * 4, helper ? 4096 : 12288);
      const uint32_t stg = sbase + (!sw ? ST0 * STAGE : helper ? ST1 * STAGE : O_U1);
      const int kbA = (f1 >> 6) + (helper ? 2 : 1) * (sw ^ flip), kbB = helper ? (f1 >> 6) + 1 : kbA;
      const int dB = helper ? d1 : d1 + 96;
      uint8_t* const uA = upin(sc->u + ((size_t)kbA * D_ + d1) * 128);
      uint8_t* const uB = upin(sc->u + ((size_t)kbB * D_ + dB) * 128);
      unsigned* const fA = pin(&sc->cnt[C_U + kbA]);
      unsigned* const fB = pin(&sc->cnt[C_U + kbB]);
      bar_sync(11 + sw, 160);
      const bool slow = sw && !helper;
      if (!slow) { if (elect()) { bulk_st(uA, stg, 96 * 128); TS(sw ? 31 : 30); } __syncwarp(); }
      bar_sync(13 + sw, 160);
      if (slow) {
        if (g2) mbar_wait(full0 + 8 * B_GO, 0);
#pragma unroll 1
        for (int i = 0; i < 20480; i += TRKB) {
          if (elect()) bulk_st(uA + i, stg + i, TRKB);
          pause(TRKC);
        }
      }
      if (elect()) {
        if (helper ? sw : !sw) bulk_st(uB, stg + 96 * 128, helper ? 96 * 128 : 64 * 128);
        bulk_commit_wait();
        red_add(fA, 1);
        if (WAITALL) red_add(&sc->cnt[C_X + 32], 1);
        if (helper && sw) red_add(fB, 1);
        if (!slow) mbar_arrive(empty0 + 8 * (sw ? ST1 : ST0));
        TS(sw ? 23 : 17);
        mbar_arrive(full0 + 8 * B_S5);
      }
      __syncwarp();
      if (sw) {
        mbar_wait(full0 + 8 * B_S5, rows);
        if (elect()) { asm volatile("fence.acq_rel.gpu;" ::: "memory"); red_add(&sc->cnt[C_X], 1); }
        __syncwarp();
      }
      if (g2) {
        if (!sw) check_tiles(true, NV2, 3, 16384 + l * 32 + (4 * (g & 1) + (g >> 1)) * 4, 10240);
        else {
          wait_cnt(&sc->cnt[C_X], NCTA * ep);
          if (elect()) mbar_arrive(full0 + 8 * B_X);
        }
      }
      __syncwarp();
    } else {
      uint64_t ready = 0;
      int st = 0, ph = 1;
#pragma unroll 1
      for (int kb = 0; kb < 32; kb++) {
        const uint8_t* src = upin(sc->h3 + ((size_t)(kb * 18 + (d1 >> 5)) << 12));
        const uint32_t dst = upin(sbase + st * STAGE + a1bytes), lb = full0 + 8 * ((kb < NV1 ? B_LAND : 0) + st);
        if (kb == NV1) { mbar_wait(full0 + 8 * B_X, 0); fence_async_glb(); ready = ~0ull; }
        if (rows && (kb >> 1) == 2) mbar_wait(full0 + 8 * (B_S4 - 4 + kb), 0);
        mbar_wait(empty0 + 8 * st, ph);
        if (elect()) mbar_expect(lb, STAGE - a1bytes);
        wait_flags(sc->cnt + C_H3, 32, (kb & 7) + (kb < 8 * H3G ? 0 : 8), 16 * ep, ready);
        if (kb == 0) CKX(5);
        if (elect()) bulk_ld(dst, src, STAGE - a1bytes, lb);
        if (kb == 0) CKX(6);
        if (kb == 5) CKX(8);
        if (kb == 8 * H3G) CKX(9);
        ring_next<false>(st, ph);
      }
      if (g2) {
        ready = 0;
        st++;
#pragma unroll 1
        for (int i = 0; i < 36; i++) {
          const int kb = kb2_order(i);
          const uint8_t* src = upin(sc->u + ((size_t)(36 * r + kb) * D_ + d2) * 128);
          const uint32_t dst = upin(sbase + st * STAGE2 + 16384), lb = full0 + 8 * ((i < NV2 ? B_LAND : 0) + st);
          if (i == NV2) { mbar_wait(full0 + 8 * B_X, 1); fence_async_glb(); ready = ~0ull; }
          mbar_wait(empty0 + 8 * st, ph);
          if (elect()) mbar_expect(lb, 18432);
          wait_flags(sc->cnt + C_U + 36 * r, 36, kb, 4 * ep, ready);
          if (elect()) {
            bulk_ld(dst, src, 18432, lb);
            if (i == GOAT) mbar_arrive(full0 + 8 * B_GO);
          }
          if (i < 6) CKX(10 + 3 * i);
          ring_next<true>(st, ph);
        }
        mbar_wait(empty0 + 8 * st, ph);
        if (elect()) {
          mbar_arrive(full0 + 8 * XST);
          mbar_expect(full0 + 8 * XST, 18432);
#pragma unroll 1
          for (int i = 0; i < 3; i++) tma2d(sbase + XST * STAGE2 + i * 6144, &maps.x1, d2 + 48 * i, s2 + 64 * (r ^ 1), full0 + 8 * XST);
        }
        __syncwarp();
      }
    }
  } else {
    asm volatile("setmaxnreg.inc.sync.aligned.u32 232;");
    const int wgu = wg;
    constexpr uint32_t sb4 = sbase >> 4;
    const int w = wp & 3;
    Ring rg = {0, 0};
    uint32_t* const x1p = sc->x1 + (size_t)(cta + 256 * wp) * 288 + l;
    const uint32_t ad = pin(sbase + (!wg ? ST0 * STAGE : helper ? ST1 * STAGE : O_U1) + (8 * (l >> 4) + (l & 7)) * 128 + (((2 * w + ((l >> 3) & 1)) ^ (l & 7)) << 4));
    const uint32_t uam = pin(g == 2 * t ? 0xfffefffeu : ~0u), uom = pin(g == 2 * t ? tag1 * 0x10001u : 0u);
    float acc[96];
    constexpr uint32_t LA = (8192 >> 4) << 16, LB = (4096 >> 4) << 16;
    {
      const int fa = f1 + (helper ? 128 : 64) * (wg ^ flip) + 16 * w + g, fb = helper ? f1 + 64 + 16 * w + g : fa;
      const float a0 = 0.5f * __bfloat162float(p.b1[fa]), a1 = 0.5f * __bfloat162float(p.b1[fa + 8]);
      const float b0 = 0.5f * __bfloat162float(p.b1[fb]), b1 = 0.5f * __bfloat162float(p.b1[fb + 8]);
#pragma unroll
      for (int i = 0; i < 96; i++) acc[i] = i < 48 ? ((i & 2) ? a1 : a0) : ((i & 2) ? b1 : b0);
      reg_fence(acc);
    }
#pragma unroll 1
    for (int live = WARM ? 0 : 1; live < 2; live++) {
    if (!live) {}
    else if (!helper) gemm_main<0>(acc, sb4 + (wgu ^ flip) * 512 + LA, 0, sb4 + 1024 + LB, wgu, rg, x1p, xr);
    else {
      float ac2[96];
#pragma unroll
      for (int i = 0; i < 96; i++) asm volatile("mov.b32 %0, %1;" : "=f"(ac2[i]) : "f"(acc[i]));
      gemm_main<1>(ac2, sb4 + (wgu ^ flip) * 1024 + LA, sb4 + 512 + LA, sb4 + 1536 + LB, wgu, rg, x1p, xr);
#pragma unroll
      for (int i = 0; i < 96; i++) asm volatile("mov.b32 %0, %1;" : "=f"(acc[i]) : "f"(ac2[i]));
    }
    if (t128 == 0) TS(wg ? 16 : 6);
    {
      float tp[2] = {0.f, 0.f};
#pragma unroll
      for (int j = 0; j < 12; j++) {
        const float* a = &acc[8 * j];
        const float k3 = j < 2 ? GK3 : fmaf(tp[j & 1], 0.0f, GK3);
        float o[8];
#pragma unroll
        for (int e = 0; e < 8; e++) {
          float z = a[e] * fmaf(a[e] * k3, a[e], GK1);
          asm("tanh.approx.f32 %0, %0;" : "+f"(z));
          if (e == GDEP) tp[j & 1] = z;
          o[e] = fmaf(a[e], z, a[e]);
        }
        stmatrix4t_if(live, ad + j * 2048, and_or(pack_bf16(o[0], o[1]), uam, uom), pack_bf16(o[2], o[3]), and_or(pack_bf16(o[4], o[5]), uam, uom), pack_bf16(o[6], o[7]));
        if (j == 5) {
          fence_async_smem();
          asm volatile("{\n.reg .pred p;\nsetp.ne.u32 p, %1, 0;\n@p bar.arrive %0, 160;\n}" ::"r"(11 + wgu), "r"(live) : "memory");
        }
        if (j == 9 && !(helper && wgu)) break;
      }
      fence_async_smem();
      asm volatile("{\n.reg .pred p;\nsetp.ne.u32 p, %1, 0;\n@p bar.arrive %0, 160;\n}" ::"r"(13 + wgu), "r"(live) : "memory");
      if (t128 == 0) TS(wg ? 29 : 28);
    }
    }
    if (g2) {
      const int mb = wgu ^ r;
      uint32_t gb[18];
      {
        float a0 = 0.f, a1 = 0.f;
        if (wgu) {
          a0 = __bfloat162float(p.b2[s2 + 64 * mb + 16 * w + g]); a1 = __bfloat162float(p.b2[s2 + 64 * mb + 16 * w + 8 + g]);
          int it = 0;
          uint32_t bad;
          do {
            bad = 0;
#pragma unroll
            for (int i = 0; i < 18; i++) {
              const uint2 v = ld_rlx2(sc->mod + 3 * D_ + d2 + 8 * i + 2 * t);
              bad |= (v.x ^ tag16) | (v.y ^ tag16);
              gb[i] = __byte_perm(v.x, v.y, 0x7632);
            }
          } while (any(bad & 0xffffu) && ++it < SPIN_MAX);
        }
#pragma unroll
        for (int i = 0; i < 72; i++) acc[i] = (i & 2) ? a1 : a0;
      }
      rg.st++;
      gemm_main<3>(acc, sb4 + mb * 512 + LA, 0, sb4 + 1024 + (1 << 16), wgu, rg, x1p, xr);
      if (t128 == 0) TS(wg ? 20 : 19);
      constexpr uint32_t sx = sbase + O_U1, so = sbase + XST * STAGE2;
      if (wgu == 0) {
        uint4* dst = sc->part + z2 * 1152 + t128;
#pragma unroll
        for (int j = 0; j < 9; j++) {
          const float* a = &acc[8 * j];
          dst[j * 128] = make_uint4(set_tag(pack_bf16(a[0], a[1]), tag1), pack_bf16(a[2], a[3]), pack_bf16(a[4], a[5]), pack_bf16(a[6], a[7]));
        }
        if (tid == 0) TS(21);
        const uint4* src = sc->part + (z2 ^ 64) * 1152 + t128;
        uint4 v[9];
        uint32_t bad;
        int it = 0;
        do {
#pragma unroll
          for (int j = 0; j < 9; j++) v[j] = ld_rlx4(src + j * 128);
          bad = or3(or3(diff2(v[0].x, v[1].x, tag1), diff2(v[2].x, v[3].x, tag1), diff2(v[4].x, v[5].x, tag1)), diff2(v[6].x, v[7].x, tag1), v[8].x ^ tag1);
        } while (any(bad & 1) && ++it < SPIN_MAX);
#pragma unroll
        for (int j = 0; j < 9; j++) sts4(sx + t128 * 16 + j * 2048, v[j].x, v[j].y, v[j].z, v[j].w);
        bar_arrive(2 + w, 64);
        if (w == 0) {
#pragma unroll 1
          for (int i = 0; i < 3; i++) {
            bar_sync(11 + i, 160);
            if (elect()) tma_st2d(&maps.out, so + i * 6144, d2 + 48 * i, s2 + 64 * (r ^ 1));
            __syncwarp();
          }
          if (elect()) { bulk_commit_wait_read(); TS(22); }
          __syncwarp();
        }
      } else {
        mbar_wait(full0 + 8 * XST, rg.ph);
        bar_sync(2 + w, 64);
        if (t128 == 0) TS(5);
        if (tid == 128 && cta == 0) sc->cnt[C_EP] = ep;
        const uint32_t xa = so + (16 * w + (l & 15)) * 96 + (l >> 4) * 16;
#pragma unroll
        for (int c = 0; c < 3; c++) {
          uint32_t pv[3][4], xv[3][4];
#pragma unroll
          for (int j = 0; j < 3; j++) {
            asm volatile("ld.shared.v4.b32 {%0,%1,%2,%3}, [%4];" : "=r"(pv[j][0]), "=r"(pv[j][1]), "=r"(pv[j][2]), "=r"(pv[j][3]) : "r"(sx + t128 * 16 + (3 * c + j) * 2048) : "memory");
            asm volatile("ldmatrix.sync.aligned.m8n8.x4.shared.b16 {%0,%1,%2,%3}, [%4];" : "=r"(xv[j][0]), "=r"(xv[j][1]), "=r"(xv[j][2]), "=r"(xv[j][3]) : "r"(xa + c * 6144 + j * 32) : "memory");
          }
#pragma unroll
          for (int j = 0; j < 3; j++) {
            const float* a = &acc[8 * (3 * c + j)];
            uint32_t o[4];
#pragma unroll
            for (int e = 0; e < 4; e++)
              o[e] = hadd2(xv[j][e], hmul2(gb[2 * (3 * c + j) + (e >> 1)], pack_bf16(a[2 * e] + bf_lo(pv[j][e]), a[2 * e + 1] + bf_hi(pv[j][e]))));
            stmatrix4(xa + c * 6144 + j * 32, o[0], o[1], o[2], o[3]);
          }
          fence_async_smem();
          asm volatile("bar.arrive %0, 160;" ::"r"(11 + c) : "memory");
        }
        if (t128 == 0) TS(7);
        __syncwarp();
      }
    }
  }
}

typedef CUresult (*EncodeFn)(CUtensorMap*, CUtensorMapDataType, cuuint32_t, void*, const cuuint64_t*, const cuuint64_t*, const cuuint32_t*,
                             const cuuint32_t*, CUtensorMapInterleave, CUtensorMapSwizzle, CUtensorMapL2promotion, CUtensorMapFloatOOBfill);

struct Dim { cuuint64_t n, stride; cuuint32_t box; };
template <int RANK>
void make_map(EncodeFn enc, CUtensorMap* m, bool words, int swz, const void* ptr, const Dim (&d)[RANK]) {
  cuuint64_t gd[RANK], gs[RANK];
  cuuint32_t bx[RANK], es[RANK];
  for (int i = 0; i < RANK; i++) { gd[i] = d[i].n; gs[i] = d[i].stride; bx[i] = d[i].box; es[i] = 1; }
  enc(m, words ? CU_TENSOR_MAP_DATA_TYPE_UINT32 : CU_TENSOR_MAP_DATA_TYPE_BFLOAT16, RANK, const_cast<void*>(ptr), gd, gs + 1, bx, es,
      CU_TENSOR_MAP_INTERLEAVE_NONE, static_cast<CUtensorMapSwizzle>(swz),
      swz == 3 ? CU_TENSOR_MAP_L2_PROMOTION_L2_256B : CU_TENSOR_MAP_L2_PROMOTION_NONE, CU_TENSOR_MAP_FLOAT_OOB_FILL_NONE);
}

}

extern "C" void kernel_launch(void* const* d_in, const int* in_sizes, int n_in, void* d_out, int out_size) {
  (void)in_sizes; (void)n_in; (void)out_size;
  static EncodeFn enc = nullptr;
  static void *sptr = nullptr, *tptr = nullptr;
  if (!enc) {
    void* f = nullptr; cudaDriverEntryPointQueryResult qr;
    cudaGetDriverEntryPoint("cuTensorMapEncodeTiled", &f, cudaEnableDefault, &qr);
    enc = reinterpret_cast<EncodeFn>(f);
    cudaFuncSetAttribute(fused_kernel, cudaFuncAttributeMaxDynamicSharedMemorySize, SMEM_BYTES);
    cudaGetSymbolAddress(&sptr, g_s);
    cudaGetSymbolAddress(&tptr, T_TAB);
  }
  Params p;
  p.x = (const __nv_bfloat16*)d_in[0]; p.wr = (const __nv_bfloat16*)d_in[1]; p.wi = (const __nv_bfloat16*)d_in[2];
  p.b1 = (const __nv_bfloat16*)d_in[5]; p.b2 = (const __nv_bfloat16*)d_in[7];
  p.c = (const __nv_bfloat16*)d_in[8]; p.wmod = (const __nv_bfloat16*)d_in[9];
  p.w1 = (const __nv_bfloat16*)d_in[4]; p.w2 = (const __nv_bfloat16*)d_in[6];
  p.s = static_cast<Scratch*>(sptr); p.tab = static_cast<const uint4*>(tptr);
  Maps maps;
  make_map<4>(enc, &maps.w1a, false, 3, p.w1, {{64, 0, 64}, {16, 128 * 2 * F_, 4}, {128, 2 * F_, 16}, {72, 128, 2}});
  make_map<4>(enc, &maps.w1b, false, 3, p.w1, {{64, 0, 64}, {16, 128 * 2 * F_, 4}, {128, 2 * F_, 16}, {72, 128, 3}});
  make_map<3>(enc, &maps.w2, false, 3, p.w2, {{64, 0, 64}, {F_, 2 * S_, 64}, {32, 128, 2}});
  make_map<2>(enc, &maps.x1, false, 0, p.s->x1, {{D_, 0, 48}, {S_, 2 * D_, 64}});
  make_map<2>(enc, &maps.out, false, 0, d_out, {{D_, 0, 48}, {S_, 2 * D_, 64}});
  make_map<2>(enc, &maps.z1, true, 0, p.s->z1, {{5120, 0, 40}, {120, 20480, 60}});
  for (int i = 0; i < 2; i++) make_map<2>(enc, &maps.z2[i], true, 0, p.s->z2, {{4800, 0, i ? 16u : 24u}, {128, 19200, 128}});
  for (int i = 0; i < 4; i++) make_map<2>(enc, &maps.wf[i], false, 2 - (i & 1), (i & 2) ? p.wi : p.wr, {{16 * DF_, 0, (i & 1) ? 16u : 32u}, {128, 32 * DF_, 128}});
  make_map<2>(enc, &maps.wm, false, 1, p.wmod, {{6 * D_, 0, 16}, {D_, 12 * D_, 192}});
  for (int i = 0; i < 2; i++) make_map<3>(enc, &maps.h3[i], true, 0, p.s->h3, {{1024, 0, 64}, {144, 4096, 18}, {4, 144 * 4096, i ? 4u - H3G : H3G}});
  fused_kernel<<<NCTA, NTHR, SMEM_BYTES, cudaStreamPerThread>>>(p, maps);
}
```

```cpp
#include <cuda_runtime.h>
#include <cuda_bf16.h>
#include <cuda.h>
#include <stdint.h>

namespace {

constexpr int S_ = 2048, D_ = 576, DF_ = 289, F_ = 4608;
constexpr int NCTA = 132, NTHR = 384;
constexpr int STAGE = 36864, NST = 6;
constexpr int STAGE2 = 34816, O_U1 = NST * STAGE2, SMEM_BYTES = 232448;
constexpr uint32_t sbase = 1024, red = sbase + NST * STAGE, full0 = sbase + SMEM_BYTES - 256, empty0 = full0 + 8 * NST;
constexpr int O_NRM = 0, O_B1 = 19456, O_Z1 = 38912, O_P2 = 59392, O_ST = 3 * STAGE;
constexpr int O_RAW = 4 * STAGE;
constexpr int O_IN = 4 * STAGE, O_Y = O_IN + 19456, O_B3 = O_IN + 38912, O_MOD = O_IN + 57344;

__device__ __align__(128) const uint32_t T_TAB[5632] = {
0x3f803f80,0xbf803f80,0x3f803f80,0xbf803f80,0x3f803f80,0xbf803f80,0x3f803f80,0xbf803f80,0x3f803f80,0xbf803f80,0x3f803f80,0xbf803f80,
0x3f803f80,0xbf803f80,0x3f803f80,0xbf803f80,0x3f7f3f80,0xbdc90000,0x3f223f35,0xbf46bf35,0x3f753f7b,0xbe95be48,0x3ef13f0e,0xbf62bf55,
0x3f623f6d,0xbef1bec4,0x3e953ec4,0xbf75bf6d,0x3f463f55,0xbf22bf0e,0x3dc93e48,0xbf7fbf7b,0x3f7b3f80,0xbe480000,0xbe480000,0xbf7bbf80,
0x3f553f6d,0xbf0ebec4,0xbf0ebec4,0xbf55bf6d,0x3f0e3f35,0xbf55bf35,0xbf55bf35,0xbf0ebf35,0x3e483ec4,0xbf7bbf6d,0xbf7bbf6d,0xbe48bec4,
0x3f753f80,0xbe950000,0xbf62bf35,0xbef1bf35,0x3f223f55,0xbf46bf0e,0xbf7fbf7b,0x3dc9be48,0x3dc93ec4,0xbf7fbf6d,0xbf46bf6d,0x3f223ec4,
0xbef1be48,0xbf62bf7b,0xbe95bf0e,0x3f753f55,0x3f6d3f80,0xbec40000,0xbf6dbf80,0x3ec40000,0x3ec43f35,0xbf6dbf35,0xbec4bf35,0x3f6d3f35,
0xbec40000,0xbf6dbf80,0x3ec40000,0x3f6d3f80,0xbf6dbf35,0xbec4bf35,0x3f6d3f35,0x3ec43f35,0x3f623f80,0xbef10000,0xbe95bf35,0x3f753f35,
0x3dc93f0e,0xbf7fbf55,0x3f223e48,0x3f463f7b,0xbf46bec4,0xbf22bf6d,0x3f7f3f6d,0xbdc93ec4,0xbf75bf7b,0x3e95be48,0x3ef13f55,0xbf62bf0e,
0x3f553f80,0xbf0e0000,0x3f0e0000,0x3f553f80,0xbe483ec4,0xbf7bbf6d,0x3f7b3f6d,0xbe483ec4,0xbf7bbf35,0xbe48bf35,0x3e483f35,0xbf7bbf35,
0xbf0ebf6d,0x3f553ec4,0xbf55bec4,0xbf0ebf6d,0x3f463f80,0xbf220000,0x3f7f3f35,0x3dc93f35,0xbef13e48,0xbf62bf7b,0x3e953f55,0xbf75bf0e,
0xbf75bf6d,0x3e95bec4,0xbf62bec4,0xbef1bf6d,0x3dc9bf0e,0x3f7f3f55,0xbf22bf7b,0x3f463e48,0x3f353f80,0xbf350000,0x3f353f80,0xbf350000,
0xbf350000,0xbf35bf80,0xbf350000,0xbf35bf80,0xbf35bf80,0x3f350000,0xbf35bf80,0x3f350000,0x3f350000,0x3f353f80,0x3f350000,0x3f353f80,
0x3f223f80,0xbf460000,0xbdc93f35,0xbf7fbf35,0xbf62be48,0xbef1bf7b,0xbf75bf55,0x3e95bf0e,0xbe95bf6d,0x3f753ec4,0x3ef1bec4,0x3f623f6d,
0x3f7f3f0e,0x3dc93f55,0x3f463f7b,0xbf223e48,0x3f0e3f80,0xbf550000,0xbf550000,0xbf0ebf80,0xbf7bbec4,0xbe48bf6d,0xbe48bf6d,0x3f7b3ec4,
0x3e48bf35,0x3f7b3f35,0x3f7b3f35,0xbe483f35,0x3f553f6d,0xbf0e3ec4,0xbf0e3ec4,0xbf55bf6d,0x3ef13f80,0xbf620000,0xbf75bf35,0x3e95bf35,
0xbf7fbf0e,0x3dc9bf55,0x3f46be48,0x3f223f7b,0x3f22bec4,0x3f463f6d,0x3dc93f6d,0xbf7fbec4,0x3e953f7b,0xbf75be48,0xbf62bf55,0x3ef1bf0e,
0x3ec43f80,0xbf6d0000,0xbec4bf80,0x3f6d0000,0xbf6dbf35,0x3ec4bf35,0x3f6d3f35,0xbec43f35,0x3f6d0000,0x3ec43f80,0xbf6d0000,0xbec4bf80,
0xbec43f35,0xbf6dbf35,0x3ec4bf35,0x3f6d3f35,0x3e953f80,0xbf750000,0x3ef1bf35,0x3f623f35,0xbf46bf55,0x3f22bf0e,0x3dc93f7b,0xbf7fbe48,
0x3f7f3ec4,0xbdc93f6d,0xbf22bf6d,0x3f46bec4,0xbf623e48,0xbef1bf7b,0x3f753f0e,0xbe953f55,0x3e483f80,0xbf7b0000,0x3f7b0000,0x3e483f80,
0xbf0ebf6d,0x3f55bec4,0xbf553ec4,0xbf0ebf6d,0x3f553f35,0xbf0e3f35,0x3f0ebf35,0x3f553f35,0xbf7bbec4,0x3e48bf6d,0xbe483f6d,0xbf7bbec4,
0x3dc93f80,0xbf7f0000,0x3f463f35,0xbf223f35,0xbe95bf7b,0x3f75be48,0xbf62bf0e,0x3ef1bf55,0x3ef13f6d,0xbf623ec4,0x3f753ec4,0xbe953f6d,
0xbf22bf55,0x3f46bf0e,0xbf7fbe48,0x3dc9bf7b,0x3f80,0xbf800000,0x3f80,0xbf800000,0xbf80,0x3f800000,0xbf80,0x3f800000,
0x3f80,0xbf800000,0x3f80,0xbf800000,0xbf80,0x3f800000,0xbf80,0x3f800000,0xbdc93f80,0xbf7f0000,0xbf463f35,0xbf22bf35,
0x3e95bf7b,0x3f753e48,0x3f62bf0e,0x3ef13f55,0xbef13f6d,0xbf62bec4,0xbf753ec4,0xbe95bf6d,0x3f22bf55,0x3f463f0e,0x3f7fbe48,0x3dc93f7b,
0xbe483f80,0xbf7b0000,0xbf7b0000,0x3e48bf80,0x3f0ebf6d,0x3f553ec4,0x3f553ec4,0xbf0e3f6d,0xbf553f35,0xbf0ebf35,0xbf0ebf35,0x3f55bf35,
0x3f7bbec4,0x3e483f6d,0x3e483f6d,0xbf7b3ec4,0xbe953f80,0xbf750000,0xbef1bf35,0x3f62bf35,0x3f46bf55,0x3f223f0e,0xbdc93f7b,0xbf7f3e48,
0xbf7f3ec4,0xbdc9bf6d,0x3f22bf6d,0x3f463ec4,0x3f623e48,0xbef13f7b,0xbf753f0e,0xbe95bf55,0xbec43f80,0xbf6d0000,0x3ec4bf80,0x3f6d0000,
0x3f6dbf35,0x3ec43f35,0xbf6d3f35,0xbec4bf35,0xbf6d0000,0x3ec4bf80,0x3f6d0000,0xbec43f80,0x3ec43f35,0xbf6d3f35,0xbec4bf35,0x3f6dbf35,
0xbef13f80,0xbf620000,0x3f75bf35,0x3e953f35,0x3f7fbf0e,0x3dc93f55,0xbf46be48,0x3f22bf7b,0xbf22bec4,0x3f46bf6d,0xbdc93f6d,0xbf7f3ec4,
0xbe953f7b,0xbf753e48,0x3f62bf55,0x3ef13f0e,0xbf0e3f80,0xbf550000,0x3f550000,0xbf0e3f80,0x3f7bbec4,0xbe483f6d,0x3e48bf6d,0x3f7bbec4,
0xbe48bf35,0x3f7bbf35,0xbf7b3f35,0xbe48bf35,0xbf553f6d,0xbf0ebec4,0x3f0e3ec4,0xbf553f6d,0xbf223f80,0xbf460000,0x3dc93f35,0xbf7f3f35,
0x3f62be48,0xbef13f7b,0x3f75bf55,0x3e953f0e,0x3e95bf6d,0x3f75bec4,0xbef1bec4,0x3f62bf6d,0xbf7f3f0e,0x3dc9bf55,0xbf463f7b,0xbf22be48,
0xbf353f80,0xbf350000,0xbf353f80,0xbf350000,0x3f350000,0xbf353f80,0x3f350000,0xbf353f80,0x3f35bf80,0x3f350000,0x3f35bf80,0x3f350000,
0xbf350000,0x3f35bf80,0xbf350000,0x3f35bf80,0xbf463f80,0xbf220000,0xbf7f3f35,0x3dc9bf35,0x3ef13e48,0xbf623f7b,0xbe953f55,0xbf753f0e,
0x3f75bf6d,0x3e953ec4,0x3f62bec4,0xbef13f6d,0xbdc9bf0e,0x3f7fbf55,0x3f22bf7b,0x3f46be48,0xbf553f80,0xbf0e0000,0xbf0e0000,0x3f55bf80,
0x3e483ec4,0xbf7b3f6d,0xbf7b3f6d,0xbe48bec4,0x3f7bbf35,0xbe483f35,0xbe483f35,0xbf7b3f35,0x3f0ebf6d,0x3f55bec4,0x3f55bec4,0xbf0e3f6d,
0xbf623f80,0xbef10000,0x3e95bf35,0x3f75bf35,0xbdc93f0e,0xbf7f3f55,0xbf223e48,0x3f46bf7b,0x3f46bec4,0xbf223f6d,0xbf7f3f6d,0xbdc9bec4,
0x3f75bf7b,0x3e953e48,0xbef13f55,0xbf623f0e,0xbf6d3f80,0xbec40000,0x3f6dbf80,0x3ec40000,0xbec43f35,0xbf6d3f35,0x3ec4bf35,0x3f6dbf35,
0x3ec40000,0xbf6d3f80,0xbec40000,0x3f6dbf80,0x3f6dbf35,0xbec43f35,0xbf6d3f35,0x3ec4bf35,0xbf753f80,0xbe950000,0x3f62bf35,0xbef13f35,
0xbf223f55,0xbf463f0e,0x3f7fbf7b,0x3dc93e48,0xbdc93ec4,0xbf7f3f6d,0x3f46bf6d,0x3f22bec4,0x3ef1be48,0xbf623f7b,0x3e95bf0e,0x3f75bf55,
0xbf7b3f80,0xbe480000,0x3e480000,0xbf7b3f80,0xbf553f6d,0xbf0e3ec4,0x3f0ebec4,0xbf553f6d,0xbf0e3f35,0xbf553f35,0x3f55bf35,0xbf0e3f35,
0xbe483ec4,0xbf7b3f6d,0x3f7bbf6d,0xbe483ec4,0xbf7f3f80,0xbdc90000,0xbf223f35,0xbf463f35,0xbf753f7b,0xbe953e48,0xbef13f0e,0xbf623f55,
0xbf623f6d,0xbef13ec4,0xbe953ec4,0xbf753f6d,0xbf463f55,0xbf223f0e,0xbdc93e48,0xbf7f3f7b,0x3f803f80,0xbf803f80,0x3f803f80,0xbf803f80,
0x3f803f80,0xbf803f80,0x3f803f80,0xbf803f80,0x3f803f80,0xbf803f80,0x3f803f80,0xbf803f80,0x3f803f80,0xbf803f80,0x3f803f80,0xbf803f80,
0xbdc90000,0xbf7fbf80,0xbf46bf35,0xbf22bf35,0xbe95be48,0xbf75bf7b,0xbf62bf55,0xbef1bf0e,0xbef1bec4,0xbf62bf6d,0xbf75bf6d,0xbe95bec4,
0xbf22bf0e,0xbf46bf55,0xbf7fbf7b,0xbdc9be48,0xbf7bbf80,0x3e480000,0x3e480000,0x3f7b3f80,0xbf55bf6d,0x3f0e3ec4,0x3f0e3ec4,0x3f553f6d,
0xbf0ebf35,0x3f553f35,0x3f553f35,0x3f0e3f35,0xbe48bec4,0x3f7b3f6d,0x3f7b3f6d,0x3e483ec4,0x3e950000,0x3f753f80,0x3ef13f35,0xbf62bf35,
0x3f463f0e,0x3f223f55,0xbdc93e48,0xbf7fbf7b,0x3f7f3f6d,0x3dc93ec4,0xbf22bec4,0xbf46bf6d,0x3f623f7b,0xbef1be48,0xbf75bf55,0xbe95bf0e,
0x3f6d3f80,0xbec40000,0xbf6dbf80,0x3ec40000,0x3ec43f35,0xbf6dbf35,0xbec4bf35,0x3f6d3f35,0xbec40000,0xbf6dbf80,0x3ec40000,0x3f6d3f80,
0xbf6dbf35,0xbec4bf35,0x3f6d3f35,0x3ec43f35,0xbef10000,0xbf62bf80,0x3f753f35,0x3e953f35,0xbf7fbf55,0xbdc9bf0e,0x3f463f7b,0xbf22be48,
0xbf22bf6d,0x3f463ec4,0xbdc93ec4,0xbf7fbf6d,0x3e95be48,0x3f753f7b,0xbf62bf0e,0xbef1bf55,0xbf55bf80,0x3f0e0000,0xbf0e0000,0xbf55bf80,
0x3e48bec4,0x3f7b3f6d,0xbf7bbf6d,0x3e48bec4,0x3f7b3f35,0x3e483f35,0xbe48bf35,0x3f7b3f35,0x3f0e3f6d,0xbf55bec4,0x3f553ec4,0x3f0e3f6d,
0x3f220000,0x3f463f80,0xbdc9bf35,0x3f7f3f35,0x3f623f7b,0xbef13e48,0x3f753f0e,0x3e953f55,0xbe953ec4,0xbf75bf6d,0x3ef13f6d,0xbf62bec4,
0xbf7fbf55,0x3dc9bf0e,0xbf46be48,0xbf22bf7b,0x3f353f80,0xbf350000,0x3f353f80,0xbf350000,0xbf350000,0xbf35bf80,0xbf350000,0xbf35bf80,
0xbf35bf80,0x3f350000,0xbf35bf80,0x3f350000,0x3f350000,0x3f353f80,0x3f350000,0x3f353f80,0xbf460000,0xbf22bf80,0xbf7fbf35,0x3dc9bf35,
0xbef1bf7b,0x3f623e48,0x3e95bf0e,0x3f753f55,0x3f753ec4,0x3e953f6d,0x3f623f6d,0xbef13ec4,0x3dc93f55,0xbf7fbf0e,0xbf223e48,0xbf46bf7b,
0xbf0ebf80,0x3f550000,0x3f550000,0x3f0e3f80,0x3f7b3ec4,0x3e483f6d,0x3e483f6d,0xbf7bbec4,0xbe483f35,0xbf7bbf35,0xbf7bbf35,0x3e48bf35,
0xbf55bf6d,0x3f0ebec4,0x3f0ebec4,0x3f553f6d,0x3f620000,0x3ef13f80,0xbe953f35,0xbf75bf35,0xbdc93f55,0xbf7fbf0e,0xbf22bf7b,0x3f46be48,
0xbf46bf6d,0x3f22bec4,0x3f7f3ec4,0x3dc93f6d,0x3f753e48,0x3e953f7b,0xbef13f0e,0xbf62bf55,0x3ec43f80,0xbf6d0000,0xbec4bf80,0x3f6d0000,
0xbf6dbf35,0x3ec4bf35,0x3f6d3f35,0xbec43f35,0x3f6d0000,0x3ec43f80,0xbf6d0000,0xbec4bf80,0xbec43f35,0xbf6dbf35,0x3ec4bf35,0x3f6d3f35,
0xbf750000,0xbe95bf80,0x3f623f35,0xbef13f35,0x3f22bf0e,0x3f463f55,0xbf7fbe48,0xbdc9bf7b,0xbdc93f6d,0xbf7fbec4,0x3f46bec4,0x3f223f6d,
0xbef1bf7b,0x3f62be48,0xbe953f55,0xbf75bf0e,0xbe48bf80,0x3f7b0000,0xbf7b0000,0xbe48bf80,0x3f0e3f6d,0xbf553ec4,0x3f55bec4,0x3f0e3f6d,
0xbf55bf35,0x3f0ebf35,0xbf0e3f35,0xbf55bf35,0x3f7b3ec4,0xbe483f6d,0x3e48bf6d,0x3f7b3ec4,0x3f7f0000,0x3dc93f80,0x3f22bf35,0x3f463f35,
0xbf753e48,0xbe95bf7b,0xbef13f55,0xbf62bf0e,0x3f62bec4,0x3ef13f6d,0x3e95bf6d,0x3f753ec4,0xbf463f0e,0xbf22bf55,0xbdc93f7b,0xbf7fbe48,
0x3f80,0xbf800000,0x3f80,0xbf800000,0xbf80,0x3f800000,0xbf80,0x3f800000,0x3f80,0xbf800000,0x3f80,0xbf800000,
0xbf80,0x3f800000,0xbf80,0x3f800000,0xbf7f0000,0x3dc9bf80,0xbf22bf35,0x3f46bf35,0x3f753e48,0xbe953f7b,0x3ef13f55,0xbf623f0e,
0xbf62bec4,0x3ef1bf6d,0xbe95bf6d,0x3f75bec4,0x3f463f0e,0xbf223f55,0x3dc93f7b,0xbf7f3e48,0x3e48bf80,0x3f7b0000,0x3f7b0000,0xbe483f80,
0xbf0e3f6d,0xbf55bec4,0xbf55bec4,0x3f0ebf6d,0x3f55bf35,0x3f0e3f35,0x3f0e3f35,0xbf553f35,0xbf7b3ec4,0xbe48bf6d,0xbe48bf6d,0x3f7bbec4,
0x3f750000,0xbe953f80,0xbf623f35,0xbef1bf35,0xbf22bf0e,0x3f46bf55,0x3f7fbe48,0xbdc93f7b,0x3dc93f6d,0xbf7f3ec4,0xbf46bec4,0x3f22bf6d,
0x3ef1bf7b,0x3f623e48,0x3e953f55,0xbf753f0e,0xbec43f80,0xbf6d0000,0x3ec4bf80,0x3f6d0000,0x3f6dbf35,0x3ec43f35,0xbf6d3f35,0xbec4bf35,
0xbf6d0000,0x3ec4bf80,0x3f6d0000,0xbec43f80,0x3ec43f35,0xbf6d3f35,0xbec4bf35,0x3f6dbf35,0xbf620000,0x3ef1bf80,0x3e953f35,0xbf753f35,
0x3dc93f55,0xbf7f3f0e,0x3f22bf7b,0x3f463e48,0x3f46bf6d,0x3f223ec4,0xbf7f3ec4,0x3dc9bf6d,0xbf753e48,0x3e95bf7b,0x3ef13f0e,0xbf623f55,
0x3f0ebf80,0x3f550000,0xbf550000,0x3f0ebf80,0xbf7b3ec4,0x3e48bf6d,0xbe483f6d,0xbf7b3ec4,0x3e483f35,0xbf7b3f35,0x3f7bbf35,0x3e483f35,
0x3f55bf6d,0x3f0e3ec4,0xbf0ebec4,0x3f55bf6d,0x3f460000,0xbf223f80,0x3f7fbf35,0x3dc93f35,0x3ef1bf7b,0x3f62be48,0xbe95bf0e,0x3f75bf55,
0xbf753ec4,0x3e95bf6d,0xbf623f6d,0xbef1bec4,0xbdc93f55,0xbf7f3f0e,0x3f223e48,0xbf463f7b,0xbf353f80,0xbf350000,0xbf353f80,0xbf350000,
0x3f350000,0xbf353f80,0x3f350000,0xbf353f80,0x3f35bf80,0x3f350000,0x3f35bf80,0x3f350000,0xbf350000,0x3f35bf80,0xbf350000,0x3f35bf80,
0xbf220000,0x3f46bf80,0x3dc9bf35,0x3f7fbf35,0xbf623f7b,0xbef1be48,0xbf753f0e,0x3e95bf55,0x3e953ec4,0xbf753f6d,0xbef13f6d,0xbf623ec4,
0x3f7fbf55,0x3dc93f0e,0x3f46be48,0xbf223f7b,0x3f55bf80,0x3f0e0000,0x3f0e0000,0xbf553f80,0xbe48bec4,0x3f7bbf6d,0x3f7bbf6d,0x3e483ec4,
0xbf7b3f35,0x3e48bf35,0x3e48bf35,0x3f7bbf35,0xbf0e3f6d,0xbf553ec4,0xbf553ec4,0x3f0ebf6d,0x3ef10000,0xbf623f80,0xbf753f35,0x3e95bf35,
0x3f7fbf55,0xbdc93f0e,0xbf463f7b,0xbf223e48,0x3f22bf6d,0x3f46bec4,0x3dc93ec4,0xbf7f3f6d,0xbe95be48,0x3f75bf7b,0x3f62bf0e,0xbef13f55,
0xbf6d3f80,0xbec40000,0x3f6dbf80,0x3ec40000,0xbec43f35,0xbf6d3f35,0x3ec4bf35,0x3f6dbf35,0x3ec40000,0xbf6d3f80,0xbec40000,0x3f6dbf80,
0x3f6dbf35,0xbec43f35,0xbf6d3f35,0x3ec4bf35,0xbe950000,0x3f75bf80,0xbef13f35,0xbf623f35,0xbf463f0e,0x3f22bf55,0x3dc93e48,0xbf7f3f7b,
0xbf7f3f6d,0x3dc9bec4,0x3f22bec4,0xbf463f6d,0xbf623f7b,0xbef13e48,0x3f75bf55,0xbe953f0e,0x3f7bbf80,0x3e480000,0xbe480000,0x3f7bbf80,
0x3f55bf6d,0x3f0ebec4,0xbf0e3ec4,0x3f55bf6d,0x3f0ebf35,0x3f55bf35,0xbf553f35,0x3f0ebf35,0x3e48bec4,0x3f7bbf6d,0xbf7b3f6d,0x3e48bec4,
0x3dc90000,0xbf7f3f80,0x3f46bf35,0xbf223f35,0x3e95be48,0xbf753f7b,0x3f62bf55,0xbef13f0e,0x3ef1bec4,0xbf623f6d,0x3f75bf6d,0xbe953ec4,
0x3f22bf0e,0xbf463f55,0x3f7fbf7b,0xbdc93e48,0x3f803f80,0xbf803f80,0x3f803f80,0xbf803f80,0x3f803f80,0xbf803f80,0x3f803f80,0xbf803f80,
0x3f803f80,0xbf803f80,0x3f803f80,0xbf803f80,0x3f803f80,0xbf803f80,0x3f803f80,0xbf803f80,0xbf7fbf80,0x3dc90000,0xbf22bf35,0x3f463f35,
0xbf75bf7b,0x3e953e48,0xbef1bf0e,0x3f623f55,0xbf62bf6d,0x3ef13ec4,0xbe95bec4,0x3f753f6d,0xbf46bf55,0x3f223f0e,0xbdc9be48,0x3f7f3f7b,
0x3f7b3f80,0xbe480000,0xbe480000,0xbf7bbf80,0x3f553f6d,0xbf0ebec4,0xbf0ebec4,0xbf55bf6d,0x3f0e3f35,0xbf55bf35,0xbf55bf35,0xbf0ebf35,
0x3e483ec4,0xbf7bbf6d,0xbf7bbf6d,0xbe48bec4,0xbf75bf80,0x3e950000,0x3f623f35,0x3ef13f35,0xbf22bf55,0x3f463f0e,0x3f7f3f7b,0xbdc93e48,
0xbdc9bec4,0x3f7f3f6d,0x3f463f6d,0xbf22bec4,0x3ef13e48,0x3f623f7b,0x3e953f0e,0xbf75bf55,0x3f6d3f80,0xbec40000,0xbf6dbf80,0x3ec40000,
0x3ec43f35,0xbf6dbf35,0xbec4bf35,0x3f6d3f35,0xbec40000,0xbf6dbf80,0x3ec40000,0x3f6d3f80,0xbf6dbf35,0xbec4bf35,0x3f6d3f35,0x3ec43f35,
0xbf62bf80,0x3ef10000,0x3e953f35,0xbf75bf35,0xbdc9bf0e,0x3f7f3f55,0xbf22be48,0xbf46bf7b,0x3f463ec4,0x3f223f6d,0xbf7fbf6d,0x3dc9bec4,
0x3f753f7b,0xbe953e48,0xbef1bf55,0x3f623f0e,0x3f553f80,0xbf0e0000,0x3f0e0000,0x3f553f80,0xbe483ec4,0xbf7bbf6d,0x3f7b3f6d,0xbe483ec4,
0xbf7bbf35,0xbe48bf35,0x3e483f35,0xbf7bbf35,0xbf0ebf6d,0x3f553ec4,0xbf55bec4,0xbf0ebf6d,0xbf46bf80,0x3f220000,0xbf7fbf35,0xbdc9bf35,
0x3ef1be48,0x3f623f7b,0xbe95bf55,0x3f753f0e,0x3f753f6d,0xbe953ec4,0x3f623ec4,0x3ef13f6d,0xbdc93f0e,0xbf7fbf55,0x3f223f7b,0xbf46be48,
0x3f353f80,0xbf350000,0x3f353f80,0xbf350000,0xbf350000,0xbf35bf80,0xbf350000,0xbf35bf80,0xbf35bf80,0x3f350000,0xbf35bf80,0x3f350000,
0x3f350000,0x3f353f80,0x3f350000,0x3f353f80,0xbf22bf80,0x3f460000,0x3dc9bf35,0x3f7f3f35,0x3f623e48,0x3ef13f7b,0x3f753f55,0xbe953f0e,
0x3e953f6d,0xbf75bec4,0xbef13ec4,0xbf62bf6d,0xbf7fbf0e,0xbdc9bf55,0xbf46bf7b,0x3f22be48,0x3f0e3f80,0xbf550000,0xbf550000,0xbf0ebf80,
0xbf7bbec4,0xbe48bf6d,0xbe48bf6d,0x3f7b3ec4,0x3e48bf35,0x3f7b3f35,0x3f7b3f35,0xbe483f35,0x3f553f6d,0xbf0e3ec4,0xbf0e3ec4,0xbf55bf6d,
0xbef1bf80,0x3f620000,0x3f753f35,0xbe953f35,0x3f7f3f0e,0xbdc93f55,0xbf463e48,0xbf22bf7b,0xbf223ec4,0xbf46bf6d,0xbdc9bf6d,0x3f7f3ec4,
0xbe95bf7b,0x3f753e48,0x3f623f55,0xbef13f0e,0x3ec43f80,0xbf6d0000,0xbec4bf80,0x3f6d0000,0xbf6dbf35,0x3ec4bf35,0x3f6d3f35,0xbec43f35,
0x3f6d0000,0x3ec43f80,0xbf6d0000,0xbec4bf80,0xbec43f35,0xbf6dbf35,0x3ec4bf35,0x3f6d3f35,0xbe95bf80,0x3f750000,0xbef13f35,0xbf62bf35,
0x3f463f55,0xbf223f0e,0xbdc9bf7b,0x3f7f3e48,0xbf7fbec4,0x3dc9bf6d,0x3f223f6d,0xbf463ec4,0x3f62be48,0x3ef13f7b,0xbf75bf0e,0x3e95bf55,
0x3e483f80,0xbf7b0000,0x3f7b0000,0x3e483f80,0xbf0ebf6d,0x3f55bec4,0xbf553ec4,0xbf0ebf6d,0x3f553f35,0xbf0e3f35,0x3f0ebf35,0x3f553f35,
0xbf7bbec4,0x3e48bf6d,0xbe483f6d,0xbf7bbec4,0xbdc9bf80,0x3f7f0000,0xbf46bf35,0x3f22bf35,0x3e953f7b,0xbf753e48,0x3f623f0e,0xbef13f55,
0xbef1bf6d,0x3f62bec4,0xbf75bec4,0x3e95bf6d,0x3f223f55,0xbf463f0e,0x3f7f3e48,0xbdc93f7b,0x3f80,0xbf800000,0x3f80,0xbf800000,
0xbf80,0x3f800000,0xbf80,0x3f800000,0x3f80,0xbf800000,0x3f80,0xbf800000,0xbf80,0x3f800000,0xbf80,0x3f800000,
0x3dc9bf80,0x3f7f0000,0x3f46bf35,0x3f223f35,0xbe953f7b,0xbf75be48,0xbf623f0e,0xbef1bf55,0x3ef1bf6d,0x3f623ec4,0x3f75bec4,0x3e953f6d,
0xbf223f55,0xbf46bf0e,0xbf7f3e48,0xbdc9bf7b,0xbe483f80,0xbf7b0000,0xbf7b0000,0x3e48bf80,0x3f0ebf6d,0x3f553ec4,0x3f553ec4,0xbf0e3f6d,
0xbf553f35,0xbf0ebf35,0xbf0ebf35,0x3f55bf35,0x3f7bbec4,0x3e483f6d,0x3e483f6d,0xbf7b3ec4,0x3e95bf80,0x3f750000,0x3ef13f35,0xbf623f35,
0xbf463f55,0xbf22bf0e,0x3dc9bf7b,0x3f7fbe48,0x3f7fbec4,0x3dc93f6d,0xbf223f6d,0xbf46bec4,0xbf62be48,0x3ef1bf7b,0x3f75bf0e,0x3e953f55,
0xbec43f80,0xbf6d0000,0x3ec4bf80,0x3f6d0000,0x3f6dbf35,0x3ec43f35,0xbf6d3f35,0xbec4bf35,0xbf6d0000,0x3ec4bf80,0x3f6d0000,0xbec43f80,
0x3ec43f35,0xbf6d3f35,0xbec4bf35,0x3f6dbf35,0x3ef1bf80,0x3f620000,0xbf753f35,0xbe95bf35,0xbf7f3f0e,0xbdc9bf55,0x3f463e48,0xbf223f7b,
0x3f223ec4,0xbf463f6d,0x3dc9bf6d,0x3f7fbec4,0x3e95bf7b,0x3f75be48,0xbf623f55,0xbef1bf0e,0xbf0e3f80,0xbf550000,0x3f550000,0xbf0e3f80,
0x3f7bbec4,0xbe483f6d,0x3e48bf6d,0x3f7bbec4,0xbe48bf35,0x3f7bbf35,0xbf7b3f35,0xbe48bf35,0xbf553f6d,0xbf0ebec4,0x3f0e3ec4,0xbf553f6d,
0x3f22bf80,0x3f460000,0xbdc9bf35,0x3f7fbf35,0xbf623e48,0x3ef1bf7b,0xbf753f55,0xbe95bf0e,0xbe953f6d,0xbf753ec4,0x3ef13ec4,0xbf623f6d,
0x3f7fbf0e,0xbdc93f55,0x3f46bf7b,0x3f223e48,0xbf353f80,0xbf350000,0xbf353f80,0xbf350000,0x3f350000,0xbf353f80,0x3f350000,0xbf353f80,
0x3f35bf80,0x3f350000,0x3f35bf80,0x3f350000,0xbf350000,0x3f35bf80,0xbf350000,0x3f35bf80,0x3f46bf80,0x3f220000,0x3f7fbf35,0xbdc93f35,
0xbef1be48,0x3f62bf7b,0x3e95bf55,0x3f75bf0e,0xbf753f6d,0xbe95bec4,0xbf623ec4,0x3ef1bf6d,0x3dc93f0e,0xbf7f3f55,0xbf223f7b,0xbf463e48,
0xbf553f80,0xbf0e0000,0xbf0e0000,0x3f55bf80,0x3e483ec4,0xbf7b3f6d,0xbf7b3f6d,0xbe48bec4,0x3f7bbf35,0xbe483f35,0xbe483f35,0xbf7b3f35,
0x3f0ebf6d,0x3f55bec4,0x3f55bec4,0xbf0e3f6d,0x3f62bf80,0x3ef10000,0xbe953f35,0xbf753f35,0x3dc9bf0e,0x3f7fbf55,0x3f22be48,0xbf463f7b,
0xbf463ec4,0x3f22bf6d,0x3f7fbf6d,0x3dc93ec4,0xbf753f7b,0xbe95be48,0x3ef1bf55,0x3f62bf0e,0xbf6d3f80,0xbec40000,0x3f6dbf80,0x3ec40000,
0xbec43f35,0xbf6d3f35,0x3ec4bf35,0x3f6dbf35,0x3ec40000,0xbf6d3f80,0xbec40000,0x3f6dbf80,0x3f6dbf35,0xbec43f35,0xbf6d3f35,0x3ec4bf35,
0x3f75bf80,0x3e950000,0xbf623f35,0x3ef1bf35,0x3f22bf55,0x3f46bf0e,0xbf7f3f7b,0xbdc9be48,0x3dc9bec4,0x3f7fbf6d,0xbf463f6d,0xbf223ec4,
0xbef13e48,0x3f62bf7b,0xbe953f0e,0xbf753f55,0xbf7b3f80,0xbe480000,0x3e480000,0xbf7b3f80,0xbf553f6d,0xbf0e3ec4,0x3f0ebec4,0xbf553f6d,
0xbf0e3f35,0xbf553f35,0x3f55bf35,0xbf0e3f35,0xbe483ec4,0xbf7b3f6d,0x3f7bbf6d,0xbe483ec4,0x3f7fbf80,0x3dc90000,0x3f22bf35,0x3f46bf35,
0x3f75bf7b,0x3e95be48,0x3ef1bf0e,0x3f62bf55,0x3f62bf6d,0x3ef1bec4,0x3e95bec4,0x3f75bf6d,0x3f46bf55,0x3f22bf0e,0x3dc9be48,0x3f7fbf7b,
0x3f803f80,0xbf803f80,0x3f803f80,0xbf803f80,0x3f803f80,0xbf803f80,0x3f803f80,0xbf803f80,0x3f803f80,0xbf803f80,0x3f803f80,0xbf803f80,
0x3f803f80,0xbf803f80,0x3f803f80,0xbf803f80,0x3dc90000,0x3f7f3f80,0x3f463f35,0x3f223f35,0x3e953e48,0x3f753f7b,0x3f623f55,0x3ef13f0e,
0x3ef13ec4,0x3f623f6d,0x3f753f6d,0x3e953ec4,0x3f223f0e,0x3f463f55,0x3f7f3f7b,0x3dc93e48,0xbf7bbf80,0x3e480000,0x3e480000,0x3f7b3f80,
0xbf55bf6d,0x3f0e3ec4,0x3f0e3ec4,0x3f553f6d,0xbf0ebf35,0x3f553f35,0x3f553f35,0x3f0e3f35,0xbe48bec4,0x3f7b3f6d,0x3f7b3f6d,0x3e483ec4,
0xbe950000,0xbf75bf80,0xbef1bf35,0x3f623f35,0xbf46bf0e,0xbf22bf55,0x3dc9be48,0x3f7f3f7b,0xbf7fbf6d,0xbdc9bec4,0x3f223ec4,0x3f463f6d,
0xbf62bf7b,0x3ef13e48,0x3f753f55,0x3e953f0e,0x3f6d3f80,0xbec40000,0xbf6dbf80,0x3ec40000,0x3ec43f35,0xbf6dbf35,0xbec4bf35,0x3f6d3f35,
0xbec40000,0xbf6dbf80,0x3ec40000,0x3f6d3f80,0xbf6dbf35,0xbec4bf35,0x3f6d3f35,0x3ec43f35,0x3ef10000,0x3f623f80,0xbf75bf35,0xbe95bf35,
0x3f7f3f55,0x3dc93f0e,0xbf46bf7b,0x3f223e48,0x3f223f6d,0xbf46bec4,0x3dc9bec4,0x3f7f3f6d,0xbe953e48,0xbf75bf7b,0x3f623f0e,0x3ef13f55,
0xbf55bf80,0x3f0e0000,0xbf0e0000,0xbf55bf80,0x3e48bec4,0x3f7b3f6d,0xbf7bbf6d,0x3e48bec4,0x3f7b3f35,0x3e483f35,0xbe48bf35,0x3f7b3f35,
0x3f0e3f6d,0xbf55bec4,0x3f553ec4,0x3f0e3f6d,0xbf220000,0xbf46bf80,0x3dc93f35,0xbf7fbf35,0xbf62bf7b,0x3ef1be48,0xbf75bf0e,0xbe95bf55,
0x3e95bec4,0x3f753f6d,0xbef1bf6d,0x3f623ec4,0x3f7f3f55,0xbdc93f0e,0x3f463e48,0x3f223f7b,0x3f353f80,0xbf350000,0x3f353f80,0xbf350000,
0xbf350000,0xbf35bf80,0xbf350000,0xbf35bf80,0xbf35bf80,0x3f350000,0xbf35bf80,0x3f350000,0x3f350000,0x3f353f80,0x3f350000,0x3f353f80,
0x3f460000,0x3f223f80,0x3f7f3f35,0xbdc93f35,0x3ef13f7b,0xbf62be48,0xbe953f0e,0xbf75bf55,0xbf75bec4,0xbe95bf6d,0xbf62bf6d,0x3ef1bec4,
0xbdc9bf55,0x3f7f3f0e,0x3f22be48,0x3f463f7b,0xbf0ebf80,0x3f550000,0x3f550000,0x3f0e3f80,0x3f7b3ec4,0x3e483f6d,0x3e483f6d,0xbf7bbec4,
0xbe483f35,0xbf7bbf35,0xbf7bbf35,0x3e48bf35,0xbf55bf6d,0x3f0ebec4,0x3f0ebec4,0x3f553f6d,0xbf620000,0xbef1bf80,0x3e95bf35,0x3f753f35,
0x3dc9bf55,0x3f7f3f0e,0x3f223f7b,0xbf463e48,0x3f463f6d,0xbf223ec4,0xbf7fbec4,0xbdc9bf6d,0xbf75be48,0xbe95bf7b,0x3ef1bf0e,0x3f623f55,
0x3ec43f80,0xbf6d0000,0xbec4bf80,0x3f6d0000,0xbf6dbf35,0x3ec4bf35,0x3f6d3f35,0xbec43f35,0x3f6d0000,0x3ec43f80,0xbf6d0000,0xbec4bf80,
0xbec43f35,0xbf6dbf35,0x3ec4bf35,0x3f6d3f35,0x3f750000,0x3e953f80,0xbf62bf35,0x3ef1bf35,0xbf223f0e,0xbf46bf55,0x3f7f3e48,0x3dc93f7b,
0x3dc9bf6d,0x3f7f3ec4,0xbf463ec4,0xbf22bf6d,0x3ef13f7b,0xbf623e48,0x3e95bf55,0x3f753f0e,0xbe48bf80,0x3f7b0000,0xbf7b0000,0xbe48bf80,
0x3f0e3f6d,0xbf553ec4,0x3f55bec4,0x3f0e3f6d,0xbf55bf35,0x3f0ebf35,0xbf0e3f35,0xbf55bf35,0x3f7b3ec4,0xbe483f6d,0x3e48bf6d,0x3f7b3ec4,
0xbf7f0000,0xbdc9bf80,0xbf223f35,0xbf46bf35,0x3f75be48,0x3e953f7b,0x3ef1bf55,0x3f623f0e,0xbf623ec4,0xbef1bf6d,0xbe953f6d,0xbf75bec4,
0x3f46bf0e,0x3f223f55,0x3dc9bf7b,0x3f7f3e48,0x3f80,0xbf800000,0x3f80,0xbf800000,0xbf80,0x3f800000,0xbf80,0x3f800000,
0x3f80,0xbf800000,0x3f80,0xbf800000,0xbf80,0x3f800000,0xbf80,0x3f800000,0x3f7f0000,0xbdc93f80,0x3f223f35,0xbf463f35,
0xbf75be48,0x3e95bf7b,0xbef1bf55,0x3f62bf0e,0x3f623ec4,0xbef13f6d,0x3e953f6d,0xbf753ec4,0xbf46bf0e,0x3f22bf55,0xbdc9bf7b,0x3f7fbe48,
0x3e48bf80,0x3f7b0000,0x3f7b0000,0xbe483f80,0xbf0e3f6d,0xbf55bec4,0xbf55bec4,0x3f0ebf6d,0x3f55bf35,0x3f0e3f35,0x3f0e3f35,0xbf553f35,
0xbf7b3ec4,0xbe48bf6d,0xbe48bf6d,0x3f7bbec4,0xbf750000,0x3e95bf80,0x3f62bf35,0x3ef13f35,0x3f223f0e,0xbf463f55,0xbf7f3e48,0x3dc9bf7b,
0xbdc9bf6d,0x3f7fbec4,0x3f463ec4,0xbf223f6d,0xbef13f7b,0xbf62be48,0xbe95bf55,0x3f75bf0e,0xbec43f80,0xbf6d0000,0x3ec4bf80,0x3f6d0000,
0x3f6dbf35,0x3ec43f35,0xbf6d3f35,0xbec4bf35,0xbf6d0000,0x3ec4bf80,0x3f6d0000,0xbec43f80,0x3ec43f35,0xbf6d3f35,0xbec4bf35,0x3f6dbf35,
0x3f620000,0xbef13f80,0xbe95bf35,0x3f75bf35,0xbdc9bf55,0x3f7fbf0e,0xbf223f7b,0xbf46be48,0xbf463f6d,0xbf22bec4,0x3f7fbec4,0xbdc93f6d,
0x3f75be48,0xbe953f7b,0xbef1bf0e,0x3f62bf55,0x3f0ebf80,0x3f550000,0xbf550000,0x3f0ebf80,0xbf7b3ec4,0x3e48bf6d,0xbe483f6d,0xbf7b3ec4,
0x3e483f35,0xbf7b3f35,0x3f7bbf35,0x3e483f35,0x3f55bf6d,0x3f0e3ec4,0xbf0ebec4,0x3f55bf6d,0xbf460000,0x3f22bf80,0xbf7f3f35,0xbdc9bf35,
0xbef13f7b,0xbf623e48,0x3e953f0e,0xbf753f55,0x3f75bec4,0xbe953f6d,0x3f62bf6d,0x3ef13ec4,0x3dc9bf55,0x3f7fbf0e,0xbf22be48,0x3f46bf7b,
0xbf353f80,0xbf350000,0xbf353f80,0xbf350000,0x3f350000,0xbf353f80,0x3f350000,0xbf353f80,0x3f35bf80,0x3f350000,0x3f35bf80,0x3f350000,
0xbf350000,0x3f35bf80,0xbf350000,0x3f35bf80,0x3f220000,0xbf463f80,0xbdc93f35,0xbf7f3f35,0x3f62bf7b,0x3ef13e48,0x3f75bf0e,0xbe953f55,
0xbe95bec4,0x3f75bf6d,0x3ef1bf6d,0x3f62bec4,0xbf7f3f55,0xbdc9bf0e,0xbf463e48,0x3f22bf7b,0x3f55bf80,0x3f0e0000,0x3f0e0000,0xbf553f80,
0xbe48bec4,0x3f7bbf6d,0x3f7bbf6d,0x3e483ec4,0xbf7b3f35,0x3e48bf35,0x3e48bf35,0x3f7bbf35,0xbf0e3f6d,0xbf553ec4,0xbf553ec4,0x3f0ebf6d,
0xbef10000,0x3f62bf80,0x3f75bf35,0xbe953f35,0xbf7f3f55,0x3dc9bf0e,0x3f46bf7b,0x3f22be48,0xbf223f6d,0xbf463ec4,0xbdc9bec4,0x3f7fbf6d,
0x3e953e48,0xbf753f7b,0xbf623f0e,0x3ef1bf55,0xbf6d3f80,0xbec40000,0x3f6dbf80,0x3ec40000,0xbec43f35,0xbf6d3f35,0x3ec4bf35,0x3f6dbf35,
0x3ec40000,0xbf6d3f80,0xbec40000,0x3f6dbf80,0x3f6dbf35,0xbec43f35,0xbf6d3f35,0x3ec4bf35,0x3e950000,0xbf753f80,0x3ef1bf35,0x3f62bf35,
0x3f46bf0e,0xbf223f55,0xbdc9be48,0x3f7fbf7b,0x3f7fbf6d,0xbdc93ec4,0xbf223ec4,0x3f46bf6d,0x3f62bf7b,0x3ef1be48,0xbf753f55,0x3e95bf0e,
0x3f7bbf80,0x3e480000,0xbe480000,0x3f7bbf80,0x3f55bf6d,0x3f0ebec4,0xbf0e3ec4,0x3f55bf6d,0x3f0ebf35,0x3f55bf35,0xbf553f35,0x3f0ebf35,
0x3e48bec4,0x3f7bbf6d,0xbf7b3f6d,0x3e48bec4,0xbdc90000,0x3f7fbf80,0xbf463f35,0x3f22bf35,0xbe953e48,0x3f75bf7b,0xbf623f55,0x3ef1bf0e,
0xbef13ec4,0x3f62bf6d,0xbf753f6d,0x3e95bec4,0xbf223f0e,0x3f46bf55,0xbf7f3f7b,0x3dc9be48,0x40003f80,0x3fb53f80,0x3f80,0xbfb53f80,
0x40004000,0xbfb50000,0x0,0xbfb5c000,0x40004000,0xbfb5c000,0x0,0x3fb50000,0x40004000,0x3fb50000,0x0,0x3fb54000,
0x3fff3f80,0x3fa23f80,0xbe49bf80,0xbfc6bf80,0x3ff53ffb,0xbfe2bec8,0xbf15bec8,0xbf71bffb,0x3fe23fed,0xbf15bfed,0xbf71bf44,0x3ff53f44,
0x3fc63fd5,0x3fff3f8e,0xbfa2bf8e,0x3e493fd5,0x3ffb3f80,0x3f8e3f80,0xbec83f80,0xbfd53f80,0x3fd53fed,0xbffbbf44,0xbf8ebf44,0xbec8bfed,
0x3f8e3fb5,0x3ec8bfb5,0xbfd5bfb5,0x3ffb3fb5,0x3ec83f44,0x3fd53fed,0xbffbbfed,0xbf8e3f44,0x3ff53f80,0x3f713f80,0xbf15bf80,0xbfe2bf80,
0x3fa23fd5,0xbfffbf8e,0xbfc6bf8e,0x3e49bfd5,0x3e493f44,0x3fa2bf44,0xbfffbfed,0x3fc63fed,0xbf71bec8,0x3f153ffb,0xbfe2bffb,0xbff5bec8,
0x3fed3f80,0x3f443f80,0xbf443f80,0xbfed3f80,0x3f443fb5,0xbfedbfb5,0xbfedbfb5,0x3f44bfb5,0xbf440000,0x3fed0000,0xbfedc000,0x3f444000,
0xbfedbfb5,0xbf443fb5,0xbf44bfb5,0xbfedbfb5,0x3fe23f80,0x3f153f80,0xbf71bf80,0xbff5bf80,0x3e493f8e,0xbfc6bfd5,0xbfffbfd5,0x3fa2bf8e,
0xbfc6bf44,0x3fff3f44,0xbfa2bfed,0xbe493fed,0xbff5bffb,0xbfe23ec8,0x3f15bec8,0xbf71bffb,0x3fd53f80,0x3ec83f80,0xbf8e3f80,0xbffb3f80,
0xbec83f44,0xbf8ebfed,0xbffbbfed,0x3fd5bf44,0xbffbbfb5,0x3fd53fb5,0xbec8bfb5,0xbf8e3fb5,0xbf8ebfed,0xbffbbf44,0x3fd53f44,0x3ec8bfed,
0x3fc63f80,0x3e493f80,0xbfa2bf80,0xbfffbf80,0xbf713ec8,0xbf15bffb,0xbfe2bffb,0x3ff5bec8,0xbff5bfed,0x3f713fed,0x3f15bf44,0xbfe23f44,
0x3e49bf8e,0xbfa2bfd5,0x3fff3fd5,0x3fc6bf8e,0x3f80,0xbfb53f80,0xc0003f80,0xbfb53f80,0xc000,0x3fb50000,0x40000000,0xbfb54000,
0x4000,0x3fb5c000,0xc0000000,0x3fb50000,0xc000,0xbfb50000,0x40000000,0x3fb5c000,0xbe493f80,0xbfc63f80,0xbfffbf80,0xbfa2bf80,
0x3f15bffb,0x3f713ec8,0x3ff53ec8,0xbfe23ffb,0xbf713fed,0x3ff5bfed,0xbfe2bf44,0x3f153f44,0x3fa2bfd5,0xbe49bf8e,0x3fc63f8e,0x3fffbfd5,
0xbec83f80,0xbfd53f80,0xbffb3f80,0xbf8e3f80,0x3f8ebfed,0x3ec83f44,0x3fd53f44,0xbffb3fed,0xbfd53fb5,0x3ffbbfb5,0xbf8ebfb5,0xbec83fb5,
0x3ffbbf44,0x3f8ebfed,0x3ec83fed,0x3fd5bf44,0xbf153f80,0xbfe23f80,0xbff5bf80,0xbf71bf80,0x3fc6bfd5,0xbe493f8e,0x3fa23f8e,0xbfff3fd5,
0xbfff3f44,0x3fc6bf44,0xbe49bfed,0xbfa23fed,0x3fe23ec8,0x3ff5bffb,0xbf713ffb,0x3f153ec8,0xbf443f80,0xbfed3f80,0xbfed3f80,0xbf443f80,
0x3fedbfb5,0xbf443fb5,0x3f443fb5,0xbfed3fb5,0xbfed0000,0x3f440000,0x3f44c000,0xbfed4000,0x3f443fb5,0x3fedbfb5,0xbfed3fb5,0xbf443fb5,
0xbf713f80,0xbff53f80,0xbfe2bf80,0xbf15bf80,0x3fffbf8e,0xbfa23fd5,0x3e493fd5,0xbfc63f8e,0xbfa2bf44,0xbe493f44,0x3fc6bfed,0xbfff3fed,
0xbf153ffb,0x3f71bec8,0xbff53ec8,0xbfe23ffb,0xbf8e3f80,0xbffb3f80,0xbfd53f80,0xbec83f80,0x3ffbbf44,0xbfd53fed,0xbec83fed,0xbf8e3f44,
0xbec8bfb5,0xbf8e3fb5,0x3ffbbfb5,0xbfd53fb5,0xbfd53fed,0xbec83f44,0xbf8ebf44,0xbffb3fed,0xbfa23f80,0xbfff3f80,0xbfc6bf80,0xbe49bf80,
0x3fe2bec8,0xbff53ffb,0xbf713ffb,0xbf153ec8,0x3f15bfed,0xbfe23fed,0x3ff5bf44,0xbf713f44,0xbfff3f8e,0xbfc63fd5,0x3e49bfd5,0xbfa23f8e,
0xc0003f80,0xbfb53f80,0x3f80,0x3fb53f80,0xc0004000,0x3fb50000,0x0,0x3fb5c000,0xc0004000,0x3fb5c000,0x0,0xbfb50000,
0xc0004000,0xbfb50000,0x0,0xbfb54000,0xbfff3f80,0xbfa23f80,0x3e49bf80,0x3fc6bf80,0xbff53ffb,0x3fe2bec8,0x3f15bec8,0x3f71bffb,
0xbfe23fed,0x3f15bfed,0x3f71bf44,0xbff53f44,0xbfc63fd5,0xbfff3f8e,0x3fa2bf8e,0xbe493fd5,0xbffb3f80,0xbf8e3f80,0x3ec83f80,0x3fd53f80,
0xbfd53fed,0x3ffbbf44,0x3f8ebf44,0x3ec8bfed,0xbf8e3fb5,0xbec8bfb5,0x3fd5bfb5,0xbffb3fb5,0xbec83f44,0xbfd53fed,0x3ffbbfed,0x3f8e3f44,
0xbff53f80,0xbf713f80,0x3f15bf80,0x3fe2bf80,0xbfa23fd5,0x3fffbf8e,0x3fc6bf8e,0xbe49bfd5,0xbe493f44,0xbfa2bf44,0x3fffbfed,0xbfc63fed,
0x3f71bec8,0xbf153ffb,0x3fe2bffb,0x3ff5bec8,0xbfed3f80,0xbf443f80,0x3f443f80,0x3fed3f80,0xbf443fb5,0x3fedbfb5,0x3fedbfb5,0xbf44bfb5,
0x3f440000,0xbfed0000,0x3fedc000,0xbf444000,0x3fedbfb5,0x3f443fb5,0x3f44bfb5,0x3fedbfb5,0xbfe23f80,0xbf153f80,0x3f71bf80,0x3ff5bf80,
0xbe493f8e,0x3fc6bfd5,0x3fffbfd5,0xbfa2bf8e,0x3fc6bf44,0xbfff3f44,0x3fa2bfed,0x3e493fed,0x3ff5bffb,0x3fe23ec8,0xbf15bec8,0x3f71bffb,
0xbfd53f80,0xbec83f80,0x3f8e3f80,0x3ffb3f80,0x3ec83f44,0x3f8ebfed,0x3ffbbfed,0xbfd5bf44,0x3ffbbfb5,0xbfd53fb5,0x3ec8bfb5,0x3f8e3fb5,
0x3f8ebfed,0x3ffbbf44,0xbfd53f44,0xbec8bfed,0xbfc63f80,0xbe493f80,0x3fa2bf80,0x3fffbf80,0x3f713ec8,0x3f15bffb,0x3fe2bffb,0xbff5bec8,
0x3ff5bfed,0xbf713fed,0xbf15bf44,0x3fe23f44,0xbe49bf8e,0x3fa2bfd5,0xbfff3fd5,0xbfc6bf8e,0x3f80,0x3fb53f80,0x40003f80,0x3fb53f80,
0xc000,0xbfb50000,0xc0000000,0x3fb54000,0x4000,0xbfb5c000,0x40000000,0xbfb50000,0xc000,0x3fb50000,0xc0000000,0xbfb5c000,
0x3e493f80,0x3fc63f80,0x3fffbf80,0x3fa2bf80,0xbf15bffb,0xbf713ec8,0xbff53ec8,0x3fe23ffb,0x3f713fed,0xbff5bfed,0x3fe2bf44,0xbf153f44,
0xbfa2bfd5,0x3e49bf8e,0xbfc63f8e,0xbfffbfd5,0x3ec83f80,0x3fd53f80,0x3ffb3f80,0x3f8e3f80,0xbf8ebfed,0xbec83f44,0xbfd53f44,0x3ffb3fed,
0x3fd53fb5,0xbffbbfb5,0x3f8ebfb5,0x3ec83fb5,0xbffbbf44,0xbf8ebfed,0xbec83fed,0xbfd5bf44,0x3f153f80,0x3fe23f80,0x3ff5bf80,0x3f71bf80,
0xbfc6bfd5,0x3e493f8e,0xbfa23f8e,0x3fff3fd5,0x3fff3f44,0xbfc6bf44,0x3e49bfed,0x3fa23fed,0xbfe23ec8,0xbff5bffb,0x3f713ffb,0xbf153ec8,
0x3f443f80,0x3fed3f80,0x3fed3f80,0x3f443f80,0xbfedbfb5,0x3f443fb5,0xbf443fb5,0x3fed3fb5,0x3fed0000,0xbf440000,0xbf44c000,0x3fed4000,
0xbf443fb5,0xbfedbfb5,0x3fed3fb5,0x3f443fb5,0x3f713f80,0x3ff53f80,0x3fe2bf80,0x3f15bf80,0xbfffbf8e,0x3fa23fd5,0xbe493fd5,0x3fc63f8e,
0x3fa2bf44,0x3e493f44,0xbfc6bfed,0x3fff3fed,0x3f153ffb,0xbf71bec8,0x3ff53ec8,0x3fe23ffb,0x3f8e3f80,0x3ffb3f80,0x3fd53f80,0x3ec83f80,
0xbffbbf44,0x3fd53fed,0x3ec83fed,0x3f8e3f44,0x3ec8bfb5,0x3f8e3fb5,0xbffbbfb5,0x3fd53fb5,0x3fd53fed,0x3ec83f44,0x3f8ebf44,0x3ffb3fed,
0x3fa23f80,0x3fff3f80,0x3fc6bf80,0x3e49bf80,0xbfe2bec8,0x3ff53ffb,0x3f713ffb,0x3f153ec8,0xbf15bfed,0x3fe23fed,0xbff5bf44,0x3f713f44,
0x3fff3f8e,0x3fc63fd5,0xbe49bfd5,0x3fa23f8e,0x40004000,0x3fb54000,0x0,0xbfb50000,0x40004000,0xbfb50000,0x0,0xbfb5c000,
0x40004000,0xbfb5c000,0x0,0x3fb50000,0x40004000,0x3fb50000,0x0,0x3fb54000,0x3fa23fb5,0xbe493fb5,0xbfc6bfb5,0xbfffbfb5,
0x3f713f8e,0xbff5bfd5,0xbfe2bfd5,0x3f15bf8e,0x3f153f44,0x3f71bf44,0xbff5bfed,0x3fe23fed,0x3e493ec8,0x3fc63ffb,0xbfffbffb,0xbfa23ec8,
0xbec80000,0xbfd50000,0xbffbc000,0xbf8ec000,0xbf8ebf44,0xbec8bfed,0xbfd5bfed,0x3ffb3f44,0xbfd5bfb5,0x3ffb3fb5,0xbf8ebfb5,0xbec83fb5,
0xbffbbfed,0xbf8e3f44,0xbec8bf44,0xbfd5bfed,0xbfe2bfb5,0xbff5bfb5,0xbf71bfb5,0x3f15bfb5,0xbfffbffb,0x3fc6bec8,0x3e49bec8,0x3fa23ffb,
0xbfc6bfed,0x3e493fed,0x3fa23f44,0xbfffbf44,0xbf15bf8e,0xbfe2bfd5,0x3ff53fd5,0x3f71bf8e,0xbfedc000,0xbf44c000,0x3f440000,0x3fed0000,
0xbf44bfb5,0x3fed3fb5,0x3fed3fb5,0xbf443fb5,0x3f440000,0xbfed0000,0x3fed4000,0xbf44c000,0x3fed3fb5,0x3f44bfb5,0x3f443fb5,0x3fed3fb5,
0xbf15bfb5,0x3f71bfb5,0x3ff53fb5,0x3fe23fb5,0x3fa23ec8,0x3e493ffb,0x3fc63ffb,0xbfffbec8,0x3fff3fed,0xbfa2bfed,0xbe493f44,0x3fc6bf44,
0x3f713fd5,0x3ff53f8e,0xbfe2bf8e,0xbf153fd5,0x3f8e0000,0x3ffb0000,0x3fd54000,0x3ec84000,0x3ffb3fed,0xbfd53f44,0xbec83f44,0xbf8ebfed,
0x3ec83fb5,0x3f8ebfb5,0xbffbbfb5,0x3fd53fb5,0xbfd5bf44,0xbec83fed,0xbf8ebfed,0xbffbbf44,0x3fff3fb5,0x3fc63fb5,0x3e493fb5,0xbfa23fb5,
0x3f153fd5,0xbfe2bf8e,0xbff5bf8e,0x3f71bfd5,0xbfe2bf44,0x3ff53f44,0xbf71bfed,0xbf153fed,0xbfa2bffb,0xbfffbec8,0x3fc63ec8,0x3e49bffb,
0x4000,0xbfb54000,0xc0000000,0xbfb50000,0xc000,0x3fb50000,0x40000000,0xbfb54000,0x4000,0x3fb5c000,0xc0000000,0x3fb50000,
0xc000,0xbfb50000,0x40000000,0x3fb5c000,0xbfc63fb5,0xbfff3fb5,0xbfa2bfb5,0x3e49bfb5,0x3fe2bf8e,0xbf153fd5,0x3f713fd5,0xbff53f8e,
0xbff53f44,0x3fe2bf44,0xbf15bfed,0xbf713fed,0x3fffbec8,0x3fa2bffb,0x3e493ffb,0x3fc6bec8,0xbffb0000,0xbf8e0000,0x3ec8c000,0x3fd5c000,
0x3fd53f44,0xbffb3fed,0xbf8e3fed,0xbec8bf44,0xbf8ebfb5,0xbec83fb5,0x3fd5bfb5,0xbffb3fb5,0x3ec83fed,0x3fd5bf44,0xbffb3f44,0xbf8e3fed,
0xbf71bfb5,0x3f15bfb5,0x3fe2bfb5,0x3ff5bfb5,0xbe493ffb,0xbfa23ec8,0xbfff3ec8,0x3fc6bffb,0x3fa2bfed,0xbfff3fed,0x3fc63f44,0xbe49bf44,
0xbff53f8e,0xbf713fd5,0xbf15bfd5,0xbfe23f8e,0x3f44c000,0x3fedc000,0x3fed0000,0x3f440000,0xbfed3fb5,0x3f44bfb5,0xbf44bfb5,0x3fedbfb5,
0x3fed0000,0xbf440000,0xbf444000,0x3fedc000,0xbf44bfb5,0xbfed3fb5,0x3fedbfb5,0x3f44bfb5,0x3ff5bfb5,0x3fe2bfb5,0x3f153fb5,0xbf713fb5,
0xbfc6bec8,0x3fffbffb,0x3fa2bffb,0x3e493ec8,0xbe493fed,0x3fc6bfed,0xbfff3f44,0x3fa2bf44,0x3fe2bfd5,0x3f15bf8e,0x3f713f8e,0x3ff5bfd5,
0x3fd50000,0x3ec80000,0xbf8e4000,0xbffb4000,0x3ec8bfed,0x3f8ebf44,0x3ffbbf44,0xbfd53fed,0xbffb3fb5,0x3fd5bfb5,0xbec8bfb5,0xbf8e3fb5,
0x3f8e3f44,0x3ffbbfed,0xbfd53fed,0xbec83f44,0x3e493fb5,0xbfa23fb5,0xbfff3fb5,0xbfc63fb5,0x3ff5bfd5,0xbf713f8e,0x3f153f8e,0xbfe23fd5,
0xbf71bf44,0xbf153f44,0x3fe2bfed,0xbff53fed,0xbfc63ffb,0xbe493ec8,0xbfa2bec8,0xbfff3ffb,0xc0004000,0xbfb54000,0x0,0x3fb50000,
0xc0004000,0x3fb50000,0x0,0x3fb5c000,0xc0004000,0x3fb5c000,0x0,0xbfb50000,0xc0004000,0xbfb50000,0x0,0xbfb54000,
0xbfa23fb5,0x3e493fb5,0x3fc6bfb5,0x3fffbfb5,0xbf713f8e,0x3ff5bfd5,0x3fe2bfd5,0xbf15bf8e,0xbf153f44,0xbf71bf44,0x3ff5bfed,0xbfe23fed,
0xbe493ec8,0xbfc63ffb,0x3fffbffb,0x3fa23ec8,0x3ec80000,0x3fd50000,0x3ffbc000,0x3f8ec000,0x3f8ebf44,0x3ec8bfed,0x3fd5bfed,0xbffb3f44,
0x3fd5bfb5,0xbffb3fb5,0x3f8ebfb5,0x3ec83fb5,0x3ffbbfed,0x3f8e3f44,0x3ec8bf44,0x3fd5bfed,0x3fe2bfb5,0x3ff5bfb5,0x3f71bfb5,0xbf15bfb5,
0x3fffbffb,0xbfc6bec8,0xbe49bec8,0xbfa23ffb,0x3fc6bfed,0xbe493fed,0xbfa23f44,0x3fffbf44,0x3f15bf8e,0x3fe2bfd5,0xbff53fd5,0xbf71bf8e,
0x3fedc000,0x3f44c000,0xbf440000,0xbfed0000,0x3f44bfb5,0xbfed3fb5,0xbfed3fb5,0x3f443fb5,0xbf440000,0x3fed0000,0xbfed4000,0x3f44c000,
0xbfed3fb5,0xbf44bfb5,0xbf443fb5,0xbfed3fb5,0x3f15bfb5,0xbf71bfb5,0xbff53fb5,0xbfe23fb5,0xbfa23ec8,0xbe493ffb,0xbfc63ffb,0x3fffbec8,
0xbfff3fed,0x3fa2bfed,0x3e493f44,0xbfc6bf44,0xbf713fd5,0xbff53f8e,0x3fe2bf8e,0x3f153fd5,0xbf8e0000,0xbffb0000,0xbfd54000,0xbec84000,
0xbffb3fed,0x3fd53f44,0x3ec83f44,0x3f8ebfed,0xbec83fb5,0xbf8ebfb5,0x3ffbbfb5,0xbfd53fb5,0x3fd5bf44,0x3ec83fed,0x3f8ebfed,0x3ffbbf44,
0xbfff3fb5,0xbfc63fb5,0xbe493fb5,0x3fa23fb5,0xbf153fd5,0x3fe2bf8e,0x3ff5bf8e,0xbf71bfd5,0x3fe2bf44,0xbff53f44,0x3f71bfed,0x3f153fed,
0x3fa2bffb,0x3fffbec8,0xbfc63ec8,0xbe49bffb,0x4000,0x3fb54000,0x40000000,0x3fb50000,0xc000,0xbfb50000,0xc0000000,0x3fb54000,
0x4000,0xbfb5c000,0x40000000,0xbfb50000,0xc000,0x3fb50000,0xc0000000,0xbfb5c000,0x3fc63fb5,0x3fff3fb5,0x3fa2bfb5,0xbe49bfb5,
0xbfe2bf8e,0x3f153fd5,0xbf713fd5,0x3ff53f8e,0x3ff53f44,0xbfe2bf44,0x3f15bfed,0x3f713fed,0xbfffbec8,0xbfa2bffb,0xbe493ffb,0xbfc6bec8,
0x3ffb0000,0x3f8e0000,0xbec8c000,0xbfd5c000,0xbfd53f44,0x3ffb3fed,0x3f8e3fed,0x3ec8bf44,0x3f8ebfb5,0x3ec83fb5,0xbfd5bfb5,0x3ffb3fb5,
0xbec83fed,0xbfd5bf44,0x3ffb3f44,0x3f8e3fed,0x3f71bfb5,0xbf15bfb5,0xbfe2bfb5,0xbff5bfb5,0x3e493ffb,0x3fa23ec8,0x3fff3ec8,0xbfc6bffb,
0xbfa2bfed,0x3fff3fed,0xbfc63f44,0x3e49bf44,0x3ff53f8e,0x3f713fd5,0x3f15bfd5,0x3fe23f8e,0xbf44c000,0xbfedc000,0xbfed0000,0xbf440000,
0x3fed3fb5,0xbf44bfb5,0x3f44bfb5,0xbfedbfb5,0xbfed0000,0x3f440000,0x3f444000,0xbfedc000,0x3f44bfb5,0x3fed3fb5,0xbfedbfb5,0xbf44bfb5,
0xbff5bfb5,0xbfe2bfb5,0xbf153fb5,0x3f713fb5,0x3fc6bec8,0xbfffbffb,0xbfa2bffb,0xbe493ec8,0x3e493fed,0xbfc6bfed,0x3fff3f44,0xbfa2bf44,
0xbfe2bfd5,0xbf15bf8e,0xbf713f8e,0xbff5bfd5,0xbfd50000,0xbec80000,0x3f8e4000,0x3ffb4000,0xbec8bfed,0xbf8ebf44,0xbffbbf44,0x3fd53fed,
0x3ffb3fb5,0xbfd5bfb5,0x3ec8bfb5,0x3f8e3fb5,0xbf8e3f44,0xbffbbfed,0x3fd53fed,0x3ec83f44,0xbe493fb5,0x3fa23fb5,0x3fff3fb5,0x3fc63fb5,
0xbff5bfd5,0x3f713f8e,0xbf153f8e,0x3fe23fd5,0x3f71bf44,0x3f153f44,0xbfe2bfed,0x3ff53fed,0x3fc63ffb,0x3e493ec8,0x3fa2bec8,0x3fff3ffb,
0x40004000,0x3fb54000,0x0,0xbfb50000,0x40004000,0xbfb50000,0x0,0xbfb5c000,0x40004000,0xbfb5c000,0x0,0x3fb50000,
0x40004000,0x3fb50000,0x0,0x3fb54000,0xbe490000,0xbfc60000,0xbfffc000,0xbfa2c000,0xbf15bec8,0xbf71bffb,0xbff5bffb,0x3fe23ec8,
0xbf71bf44,0x3ff53f44,0xbfe2bfed,0x3f153fed,0xbfa2bf8e,0x3e493fd5,0xbfc6bfd5,0xbfffbf8e,0xbffbc000,0xbf8ec000,0x3ec80000,0x3fd50000,
0xbfd5bfed,0x3ffb3f44,0x3f8e3f44,0x3ec83fed,0xbf8ebfb5,0xbec83fb5,0x3fd53fb5,0xbffbbfb5,0xbec8bf44,0xbfd5bfed,0x3ffb3fed,0x3f8ebf44,
0x3f150000,0x3fe20000,0x3ff54000,0x3f714000,0x3fc63f8e,0xbe493fd5,0x3fa23fd5,0xbfffbf8e,0x3fff3fed,0xbfc6bfed,0x3e493f44,0x3fa2bf44,
0x3fe23ffb,0x3ff53ec8,0xbf71bec8,0x3f153ffb,0x3fed4000,0x3f444000,0xbf440000,0xbfed0000,0x3f443fb5,0xbfedbfb5,0xbfedbfb5,0x3f44bfb5,
0xbf440000,0x3fed0000,0xbfedc000,0x3f444000,0xbfedbfb5,0xbf443fb5,0xbf44bfb5,0xbfedbfb5,0xbf710000,0xbff50000,0xbfe2c000,0xbf15c000,
0xbfffbfd5,0x3fa2bf8e,0xbe49bf8e,0x3fc63fd5,0xbfa2bfed,0xbe493fed,0x3fc63f44,0xbfffbf44,0x3f15bec8,0xbf71bffb,0x3ff53ffb,0x3fe2bec8,
0xbfd5c000,0xbec8c000,0x3f8e0000,0x3ffb0000,0x3ec8bf44,0x3f8e3fed,0x3ffb3fed,0xbfd53f44,0x3ffb3fb5,0xbfd5bfb5,0x3ec83fb5,0x3f8ebfb5,
0x3f8e3fed,0x3ffb3f44,0xbfd5bf44,0xbec83fed,0x3fa20000,0x3fff0000,0x3fc64000,0x3e494000,0x3fe23ffb,0xbff53ec8,0xbf713ec8,0xbf15bffb,
0xbf153f44,0x3fe2bf44,0xbff5bfed,0x3f713fed,0xbfffbfd5,0xbfc63f8e,0x3e49bf8e,0xbfa2bfd5,0x4000,0xbfb54000,0xc0000000,0xbfb50000,
0xc000,0x3fb50000,0x40000000,0xbfb54000,0x4000,0x3fb5c000,0xc0000000,0x3fb50000,0xc000,0xbfb50000,0x40000000,0x3fb5c000,
0xbfff0000,0xbfa20000,0x3e49c000,0x3fc6c000,0x3ff53ec8,0xbfe23ffb,0xbf153ffb,0xbf71bec8,0xbfe2bf44,0x3f153f44,0x3f71bfed,0xbff53fed,
0x3fc63f8e,0x3fffbfd5,0xbfa23fd5,0x3e493f8e,0x3ec8c000,0x3fd5c000,0x3ffb0000,0x3f8e0000,0xbf8e3fed,0xbec8bf44,0xbfd5bf44,0x3ffbbfed,
0x3fd5bfb5,0xbffb3fb5,0x3f8e3fb5,0x3ec8bfb5,0xbffb3f44,0xbf8e3fed,0xbec8bfed,0xbfd53f44,0x3ff50000,0x3f710000,0xbf154000,0xbfe24000,
0xbfa2bf8e,0x3fffbfd5,0x3fc6bfd5,0xbe493f8e,0x3e493fed,0x3fa2bfed,0xbfff3f44,0x3fc6bf44,0x3f71bffb,0xbf15bec8,0x3fe23ec8,0x3ff5bffb,
0xbf444000,0xbfed4000,0xbfed0000,0xbf440000,0x3fedbfb5,0xbf443fb5,0x3f443fb5,0xbfed3fb5,0xbfed0000,0x3f440000,0x3f44c000,0xbfed4000,
0x3f443fb5,0x3fedbfb5,0xbfed3fb5,0xbf443fb5,0xbfe20000,0xbf150000,0x3f71c000,0x3ff5c000,0x3e493fd5,0xbfc63f8e,0xbfff3f8e,0x3fa2bfd5,
0x3fc6bfed,0xbfff3fed,0x3fa23f44,0x3e49bf44,0xbff53ec8,0xbfe23ffb,0x3f15bffb,0xbf713ec8,0x3f8ec000,0x3ffbc000,0x3fd50000,0x3ec80000,
0xbffb3f44,0x3fd5bfed,0x3ec8bfed,0x3f8ebf44,0x3ec83fb5,0x3f8ebfb5,0xbffb3fb5,0x3fd5bfb5,0x3fd5bfed,0x3ec8bf44,0x3f8e3f44,0x3ffbbfed,
0x3fc60000,0x3e490000,0xbfa24000,0xbfff4000,0x3f71bffb,0x3f15bec8,0x3fe2bec8,0xbff53ffb,0xbff53f44,0x3f71bf44,0x3f15bfed,0xbfe23fed,
0xbe493fd5,0x3fa2bf8e,0xbfff3f8e,0xbfc63fd5,0xc0004000,0xbfb54000,0x0,0x3fb50000,0xc0004000,0x3fb50000,0x0,0x3fb5c000,
0xc0004000,0x3fb5c000,0x0,0xbfb50000,0xc0004000,0xbfb50000,0x0,0xbfb54000,0x3e490000,0x3fc60000,0x3fffc000,0x3fa2c000,
0x3f15bec8,0x3f71bffb,0x3ff5bffb,0xbfe23ec8,0x3f71bf44,0xbff53f44,0x3fe2bfed,0xbf153fed,0x3fa2bf8e,0xbe493fd5,0x3fc6bfd5,0x3fffbf8e,
0x3ffbc000,0x3f8ec000,0xbec80000,0xbfd50000,0x3fd5bfed,0xbffb3f44,0xbf8e3f44,0xbec83fed,0x3f8ebfb5,0x3ec83fb5,0xbfd53fb5,0x3ffbbfb5,
0x3ec8bf44,0x3fd5bfed,0xbffb3fed,0xbf8ebf44,0xbf150000,0xbfe20000,0xbff54000,0xbf714000,0xbfc63f8e,0x3e493fd5,0xbfa23fd5,0x3fffbf8e,
0xbfff3fed,0x3fc6bfed,0xbe493f44,0xbfa2bf44,0xbfe23ffb,0xbff53ec8,0x3f71bec8,0xbf153ffb,0xbfed4000,0xbf444000,0x3f440000,0x3fed0000,
0xbf443fb5,0x3fedbfb5,0x3fedbfb5,0xbf44bfb5,0x3f440000,0xbfed0000,0x3fedc000,0xbf444000,0x3fedbfb5,0x3f443fb5,0x3f44bfb5,0x3fedbfb5,
0x3f710000,0x3ff50000,0x3fe2c000,0x3f15c000,0x3fffbfd5,0xbfa2bf8e,0x3e49bf8e,0xbfc63fd5,0x3fa2bfed,0x3e493fed,0xbfc63f44,0x3fffbf44,
0xbf15bec8,0x3f71bffb,0xbff53ffb,0xbfe2bec8,0x3fd5c000,0x3ec8c000,0xbf8e0000,0xbffb0000,0xbec8bf44,0xbf8e3fed,0xbffb3fed,0x3fd53f44,
0xbffb3fb5,0x3fd5bfb5,0xbec83fb5,0xbf8ebfb5,0xbf8e3fed,0xbffb3f44,0x3fd5bf44,0x3ec83fed,0xbfa20000,0xbfff0000,0xbfc64000,0xbe494000,
0xbfe23ffb,0x3ff53ec8,0x3f713ec8,0x3f15bffb,0x3f153f44,0xbfe2bf44,0x3ff5bfed,0xbf713fed,0x3fffbfd5,0x3fc63f8e,0xbe49bf8e,0x3fa2bfd5,
0x4000,0x3fb54000,0x40000000,0x3fb50000,0xc000,0xbfb50000,0xc0000000,0x3fb54000,0x4000,0xbfb5c000,0x40000000,0xbfb50000,
0xc000,0x3fb50000,0xc0000000,0xbfb5c000,0x3fff0000,0x3fa20000,0xbe49c000,0xbfc6c000,0xbff53ec8,0x3fe23ffb,0x3f153ffb,0x3f71bec8,
0x3fe2bf44,0xbf153f44,0xbf71bfed,0x3ff53fed,0xbfc63f8e,0xbfffbfd5,0x3fa23fd5,0xbe493f8e,0xbec8c000,0xbfd5c000,0xbffb0000,0xbf8e0000,
0x3f8e3fed,0x3ec8bf44,0x3fd5bf44,0xbffbbfed,0xbfd5bfb5,0x3ffb3fb5,0xbf8e3fb5,0xbec8bfb5,0x3ffb3f44,0x3f8e3fed,0x3ec8bfed,0x3fd53f44,
0xbff50000,0xbf710000,0x3f154000,0x3fe24000,0x3fa2bf8e,0xbfffbfd5,0xbfc6bfd5,0x3e493f8e,0xbe493fed,0xbfa2bfed,0x3fff3f44,0xbfc6bf44,
0xbf71bffb,0x3f15bec8,0xbfe23ec8,0xbff5bffb,0x3f444000,0x3fed4000,0x3fed0000,0x3f440000,0xbfedbfb5,0x3f443fb5,0xbf443fb5,0x3fed3fb5,
0x3fed0000,0xbf440000,0xbf44c000,0x3fed4000,0xbf443fb5,0xbfedbfb5,0x3fed3fb5,0x3f443fb5,0x3fe20000,0x3f150000,0xbf71c000,0xbff5c000,
0xbe493fd5,0x3fc63f8e,0x3fff3f8e,0xbfa2bfd5,0xbfc6bfed,0x3fff3fed,0xbfa23f44,0xbe49bf44,0x3ff53ec8,0x3fe23ffb,0xbf15bffb,0x3f713ec8,
0xbf8ec000,0xbffbc000,0xbfd50000,0xbec80000,0x3ffb3f44,0xbfd5bfed,0xbec8bfed,0xbf8ebf44,0xbec83fb5,0xbf8ebfb5,0x3ffb3fb5,0xbfd5bfb5,
0xbfd5bfed,0xbec8bf44,0xbf8e3f44,0xbffbbfed,0xbfc60000,0xbe490000,0x3fa24000,0x3fff4000,0xbf71bffb,0xbf15bec8,0xbfe2bec8,0x3ff53ffb,
0x3ff53f44,0xbf71bf44,0xbf15bfed,0x3fe23fed,0x3e493fd5,0xbfa2bf8e,0x3fff3f8e,0x3fc63fd5,0x40004000,0x3fb54000,0x0,0xbfb50000,
0x40004000,0xbfb50000,0x0,0xbfb5c000,0x40004000,0xbfb5c000,0x0,0x3fb50000,0x40004000,0x3fb50000,0x0,0x3fb54000,
0xbfc6bfb5,0xbfffbfb5,0xbfa2bfb5,0x3e49bfb5,0xbfe2bfd5,0x3f15bf8e,0xbf71bf8e,0x3ff53fd5,0xbff5bfed,0x3fe23fed,0xbf15bf44,0xbf713f44,
0xbfffbffb,0xbfa23ec8,0xbe49bec8,0xbfc6bffb,0x3ec80000,0x3fd50000,0x3ffb4000,0x3f8e4000,0x3f8e3f44,0x3ec83fed,0x3fd53fed,0xbffbbf44,
0x3fd53fb5,0xbffbbfb5,0x3f8e3fb5,0x3ec8bfb5,0x3ffb3fed,0x3f8ebf44,0x3ec83f44,0x3fd53fed,0x3f713fb5,0xbf153fb5,0xbfe2bfb5,0xbff5bfb5,
0xbe493ec8,0xbfa2bffb,0xbfffbffb,0x3fc6bec8,0xbfa2bf44,0x3fff3f44,0xbfc6bfed,0x3e493fed,0xbff5bfd5,0xbf713f8e,0xbf15bf8e,0xbfe2bfd5,
0xbfedc000,0xbf44c000,0x3f440000,0x3fed0000,0xbf44bfb5,0x3fed3fb5,0x3fed3fb5,0xbf443fb5,0x3f440000,0xbfed0000,0x3fed4000,0xbf44c000,
0x3fed3fb5,0x3f44bfb5,0x3f443fb5,0x3fed3fb5,0x3ff53fb5,0x3fe23fb5,0x3f153fb5,0xbf713fb5,0x3fc63ffb,0xbfffbec8,0xbfa2bec8,0xbe49bffb,
0xbe493f44,0x3fc6bf44,0xbfffbfed,0x3fa23fed,0xbfe2bf8e,0xbf153fd5,0xbf71bfd5,0xbff5bf8e,0xbf8e0000,0xbffb0000,0xbfd5c000,0xbec8c000,
0xbffbbfed,0x3fd5bf44,0x3ec8bf44,0x3f8e3fed,0xbec8bfb5,0xbf8e3fb5,0x3ffb3fb5,0xbfd5bfb5,0x3fd53f44,0x3ec8bfed,0x3f8e3fed,0x3ffb3f44,
0xbe49bfb5,0x3fa2bfb5,0x3fff3fb5,0x3fc63fb5,0x3ff53f8e,0xbf713fd5,0x3f153fd5,0xbfe2bf8e,0x3f713fed,0x3f15bfed,0xbfe2bf44,0x3ff53f44,
0xbfc6bec8,0xbe493ffb,0xbfa2bffb,0xbfffbec8,0x4000,0xbfb54000,0xc0000000,0xbfb50000,0xc000,0x3fb50000,0x40000000,0xbfb54000,
0x4000,0x3fb5c000,0xc0000000,0x3fb50000,0xc000,0xbfb50000,0x40000000,0x3fb5c000,0xbfa2bfb5,0x3e49bfb5,0x3fc6bfb5,0x3fffbfb5,
0x3f713fd5,0xbff53f8e,0xbfe23f8e,0x3f15bfd5,0xbf15bfed,0xbf713fed,0x3ff5bf44,0xbfe23f44,0x3e493ffb,0x3fc6bec8,0xbfff3ec8,0xbfa23ffb,
0x3ffb0000,0x3f8e0000,0xbec84000,0xbfd54000,0xbfd5bf44,0x3ffbbfed,0x3f8ebfed,0x3ec83f44,0x3f8e3fb5,0x3ec8bfb5,0xbfd53fb5,0x3ffbbfb5,
0xbec8bfed,0xbfd53f44,0x3ffbbf44,0x3f8ebfed,0xbfe23fb5,0xbff53fb5,0xbf71bfb5,0x3f15bfb5,0x3fffbec8,0xbfc63ffb,0xbe493ffb,0xbfa23ec8,
0xbfc6bf44,0x3e493f44,0x3fa2bfed,0xbfff3fed,0x3f153fd5,0x3fe2bf8e,0xbff53f8e,0xbf713fd5,0x3f44c000,0x3fedc000,0x3fed0000,0x3f440000,
0xbfed3fb5,0x3f44bfb5,0xbf44bfb5,0x3fedbfb5,0x3fed0000,0xbf440000,0xbf444000,0x3fedc000,0xbf44bfb5,0xbfed3fb5,0x3fedbfb5,0x3f44bfb5,
0x3f153fb5,0xbf713fb5,0xbff53fb5,0xbfe23fb5,0x3fa2bffb,0x3e493ec8,0x3fc63ec8,0xbfff3ffb,0xbfff3f44,0x3fa2bf44,0x3e49bfed,0xbfc63fed,
0x3f713f8e,0x3ff5bfd5,0xbfe23fd5,0xbf153f8e,0xbfd50000,0xbec80000,0x3f8ec000,0x3ffbc000,0xbec83fed,0xbf8e3f44,0xbffb3f44,0x3fd5bfed,
0x3ffbbfb5,0xbfd53fb5,0x3ec83fb5,0x3f8ebfb5,0xbf8ebf44,0xbffb3fed,0x3fd5bfed,0x3ec8bf44,0x3fffbfb5,0x3fc6bfb5,0x3e493fb5,0xbfa23fb5,
0xbf15bf8e,0x3fe2bfd5,0x3ff5bfd5,0xbf713f8e,0xbfe23fed,0x3ff5bfed,0xbf71bf44,0xbf153f44,0x3fa23ec8,0x3fffbffb,0xbfc63ffb,0xbe493ec8,
0xc0004000,0xbfb54000,0x0,0x3fb50000,0xc0004000,0x3fb50000,0x0,0x3fb5c000,0xc0004000,0x3fb5c000,0x0,0xbfb50000,
0xc0004000,0xbfb50000,0x0,0xbfb54000,0x3fc6bfb5,0x3fffbfb5,0x3fa2bfb5,0xbe49bfb5,0x3fe2bfd5,0xbf15bf8e,0x3f71bf8e,0xbff53fd5,
0x3ff5bfed,0xbfe23fed,0x3f15bf44,0x3f713f44,0x3fffbffb,0x3fa23ec8,0x3e49bec8,0x3fc6bffb,0xbec80000,0xbfd50000,0xbffb4000,0xbf8e4000,
0xbf8e3f44,0xbec83fed,0xbfd53fed,0x3ffbbf44,0xbfd53fb5,0x3ffbbfb5,0xbf8e3fb5,0xbec8bfb5,0xbffb3fed,0xbf8ebf44,0xbec83f44,0xbfd53fed,
0xbf713fb5,0x3f153fb5,0x3fe2bfb5,0x3ff5bfb5,0x3e493ec8,0x3fa2bffb,0x3fffbffb,0xbfc6bec8,0x3fa2bf44,0xbfff3f44,0x3fc6bfed,0xbe493fed,
0x3ff5bfd5,0x3f713f8e,0x3f15bf8e,0x3fe2bfd5,0x3fedc000,0x3f44c000,0xbf440000,0xbfed0000,0x3f44bfb5,0xbfed3fb5,0xbfed3fb5,0x3f443fb5,
0xbf440000,0x3fed0000,0xbfed4000,0x3f44c000,0xbfed3fb5,0xbf44bfb5,0xbf443fb5,0xbfed3fb5,0xbff53fb5,0xbfe23fb5,0xbf153fb5,0x3f713fb5,
0xbfc63ffb,0x3fffbec8,0x3fa2bec8,0x3e49bffb,0x3e493f44,0xbfc6bf44,0x3fffbfed,0xbfa23fed,0x3fe2bf8e,0x3f153fd5,0x3f71bfd5,0x3ff5bf8e,
0x3f8e0000,0x3ffb0000,0x3fd5c000,0x3ec8c000,0x3ffbbfed,0xbfd5bf44,0xbec8bf44,0xbf8e3fed,0x3ec8bfb5,0x3f8e3fb5,0xbffb3fb5,0x3fd5bfb5,
0xbfd53f44,0xbec8bfed,0xbf8e3fed,0xbffb3f44,0x3e49bfb5,0xbfa2bfb5,0xbfff3fb5,0xbfc63fb5,0xbff53f8e,0x3f713fd5,0xbf153fd5,0x3fe2bf8e,
0xbf713fed,0xbf15bfed,0x3fe2bf44,0xbff53f44,0x3fc6bec8,0x3e493ffb,0x3fa2bffb,0x3fffbec8,0x4000,0x3fb54000,0x40000000,0x3fb50000,
0xc000,0xbfb50000,0xc0000000,0x3fb54000,0x4000,0xbfb5c000,0x40000000,0xbfb50000,0xc000,0x3fb50000,0xc0000000,0xbfb5c000,
0x3fa2bfb5,0xbe49bfb5,0xbfc6bfb5,0xbfffbfb5,0xbf713fd5,0x3ff53f8e,0x3fe23f8e,0xbf15bfd5,0x3f15bfed,0x3f713fed,0xbff5bf44,0x3fe23f44,
0xbe493ffb,0xbfc6bec8,0x3fff3ec8,0x3fa23ffb,0xbffb0000,0xbf8e0000,0x3ec84000,0x3fd54000,0x3fd5bf44,0xbffbbfed,0xbf8ebfed,0xbec83f44,
0xbf8e3fb5,0xbec8bfb5,0x3fd53fb5,0xbffbbfb5,0x3ec8bfed,0x3fd53f44,0xbffbbf44,0xbf8ebfed,0x3fe23fb5,0x3ff53fb5,0x3f71bfb5,0xbf15bfb5,
0xbfffbec8,0x3fc63ffb,0x3e493ffb,0x3fa23ec8,0x3fc6bf44,0xbe493f44,0xbfa2bfed,0x3fff3fed,0xbf153fd5,0xbfe2bf8e,0x3ff53f8e,0x3f713fd5,
0xbf44c000,0xbfedc000,0xbfed0000,0xbf440000,0x3fed3fb5,0xbf44bfb5,0x3f44bfb5,0xbfedbfb5,0xbfed0000,0x3f440000,0x3f444000,0xbfedc000,
0x3f44bfb5,0x3fed3fb5,0xbfedbfb5,0xbf44bfb5,0xbf153fb5,0x3f713fb5,0x3ff53fb5,0x3fe23fb5,0xbfa2bffb,0xbe493ec8,0xbfc63ec8,0x3fff3ffb,
0x3fff3f44,0xbfa2bf44,0xbe49bfed,0x3fc63fed,0xbf713f8e,0xbff5bfd5,0x3fe23fd5,0x3f153f8e,0x3fd50000,0x3ec80000,0xbf8ec000,0xbffbc000,
0x3ec83fed,0x3f8e3f44,0x3ffb3f44,0xbfd5bfed,0xbffbbfb5,0x3fd53fb5,0xbec83fb5,0xbf8ebfb5,0x3f8ebf44,0x3ffb3fed,0xbfd5bfed,0xbec8bf44,
0xbfffbfb5,0xbfc6bfb5,0xbe493fb5,0x3fa23fb5,0x3f15bf8e,0xbfe2bfd5,0xbff5bfd5,0x3f713f8e,0x3fe23fed,0xbff5bfed,0x3f71bf44,0x3f153f44,
0xbfa23ec8,0xbfffbffb,0x3fc63ffb,0x3e493ec8,0x80003f80,0x3f800000,0x80003f80,0x3f800000,0x80003f80,0x3f800000,0x80003f80,0x3f800000,
0x80003f80,0x3f800000,0x80003f80,0x3f800000,0x80003f80,0x3f800000,0x80003f80,0x3f800000,0x80003f80,0x3f800000,0x8000bf80,0xbf800000,
0x3f353f35,0x3f35bf35,0xbf35bf35,0xbf353f35,0x3f800000,0xbf80,0xbf800000,0x3f80,0x3f35bf35,0xbf35bf35,0xbf353f35,0x3f353f35,
0x80003f80,0x3f800000,0x80003f80,0x3f800000,0x3f800000,0xbf80,0x3f800000,0xbf80,0x8000bf80,0xbf800000,0x8000bf80,0xbf800000,
0xbf800000,0x3f80,0xbf800000,0x3f80,0x80003f80,0x3f800000,0x8000bf80,0xbf800000,0x3f35bf35,0xbf35bf35,0xbf353f35,0x3f353f35,
0xbf800000,0x3f80,0x3f800000,0xbf80,0x3f353f35,0x3f35bf35,0xbf35bf35,0xbf353f35,0x80003f80,0x3f800000,0x80003f80,0x3f800000,
0x8000bf80,0xbf800000,0x8000bf80,0xbf800000,0x80003f80,0x3f800000,0x80003f80,0x3f800000,0x8000bf80,0xbf800000,0x8000bf80,0xbf800000,
0x80003f80,0x3f800000,0x8000bf80,0xbf800000,0xbf35bf35,0xbf353f35,0x3f353f35,0x3f35bf35,0x3f800000,0xbf80,0xbf800000,0x3f80,
0xbf353f35,0x3f353f35,0x3f35bf35,0xbf35bf35,0x80003f80,0x3f800000,0x80003f80,0x3f800000,0xbf800000,0x3f80,0xbf800000,0x3f80,
0x8000bf80,0xbf800000,0x8000bf80,0xbf800000,0x3f800000,0xbf80,0x3f800000,0xbf80,0x80003f80,0x3f800000,0x8000bf80,0xbf800000,
0xbf353f35,0x3f353f35,0x3f35bf35,0xbf35bf35,0xbf800000,0x3f80,0x3f800000,0xbf80,0xbf35bf35,0xbf353f35,0x3f353f35,0x3f35bf35,
0x3f803f80,0x80008000,0x80008000,0xbf80bf80,0x3f803f80,0x80008000,0x80008000,0xbf80bf80,0x3f803f80,0x80008000,0x80008000,0xbf80bf80,
0x3f803f80,0x80008000,0x80008000,0xbf80bf80,0x3f353f80,0x3f358000,0x3f358000,0xbf35bf80,0xbf350000,0x3f353f80,0x3f353f80,0x3f358000,
0xbf35bf80,0xbf358000,0xbf358000,0x3f353f80,0x3f350000,0xbf35bf80,0xbf35bf80,0xbf358000,0x3f80,0x3f808000,0x3f808000,0x8000bf80,
0xbf80,0xbf808000,0xbf808000,0x80003f80,0x3f80,0x3f808000,0x3f808000,0x8000bf80,0xbf80,0xbf808000,0xbf808000,0x80003f80,
0xbf353f80,0x3f358000,0x3f358000,0x3f35bf80,0x3f350000,0x3f35bf80,0x3f35bf80,0xbf358000,0x3f35bf80,0xbf358000,0xbf358000,0xbf353f80,
0xbf350000,0xbf353f80,0xbf353f80,0x3f358000,0xbf803f80,0x80008000,0x80008000,0x3f80bf80,0xbf803f80,0x80008000,0x80008000,0x3f80bf80,
0xbf803f80,0x80008000,0x80008000,0x3f80bf80,0xbf803f80,0x80008000,0x80008000,0x3f80bf80,0xbf353f80,0xbf358000,0xbf358000,0x3f35bf80,
0x3f350000,0xbf353f80,0xbf353f80,0xbf358000,0x3f35bf80,0x3f358000,0x3f358000,0xbf353f80,0xbf350000,0x3f35bf80,0x3f35bf80,0x3f358000,
0x3f80,0xbf808000,0xbf808000,0x8000bf80,0xbf80,0x3f808000,0x3f808000,0x80003f80,0x3f80,0xbf808000,0xbf808000,0x8000bf80,
0xbf80,0x3f808000,0x3f808000,0x80003f80,0x3f353f80,0xbf358000,0xbf358000,0xbf35bf80,0xbf350000,0xbf35bf80,0xbf35bf80,0x3f358000,
0xbf35bf80,0x3f358000,0x3f358000,0x3f353f80,0x3f350000,0x3f353f80,0x3f353f80,0xbf358000,0x3f800000,0x0,0x3f800000,0x0,
0x3f800000,0x0,0x3f800000,0x0,0x3f800000,0x0,0x3f800000,0x0,0x3f800000,0x0,0x3f800000,0x0,
0x3f800000,0x0,0x3f7fb10f,0xbd48fb30,0x3f7ec46d,0xbdc8bd36,0x3f7d3aac,0xbe164083,0x3f7b14be,0xbe47c5c2,0x3f7853f8,0xbe78cfcc,
0x3f74fa0b,0xbe94a031,0x3f710908,0xbeac7cd4,0x3f800000,0x0,0x3f7ec46d,0xbdc8bd36,0x3f7b14be,0xbe47c5c2,0x3f74fa0b,0xbe94a031,
0x3f6c835e,0xbec3ef15,0x3f61c598,0xbef15aea,0x3f54db31,0xbf0e39da,0x3f45e403,0xbf226799,0x3f800000,0x0,0x3f7d3aac,0xbe164083,
0x3f74fa0b,0xbe94a031,0x3f676bd8,0xbedae880,0x3f54db31,0xbf0e39da,0x3f3daef9,0xbf2beb4a,0x3f226799,0xbf45e403,0x3f039c3d,0xbf5b941a,
0x3f800000,0x0,0x3f7b14be,0xbe47c5c2,0x3f6c835e,0xbec3ef15,0x3f54db31,0xbf0e39da,0x3f3504f3,0xbf3504f3,0x3f0e39da,0xbf54db31,
0x3ec3ef15,0xbf6c835e,0x3e47c5c2,0xbf7b14be,0x3f800000,0x0,0x3f7853f8,0xbe78cfcc,0x3f61c598,0xbef15aea,0x3f3daef9,0xbf2beb4a,
0x3f0e39da,0xbf54db31,0x3eac7cd4,0xbf710908,0x3dc8bd36,0xbf7ec46d,0xbe164083,0xbf7d3aac,0x3f800000,0x0,0x3f74fa0b,0xbe94a031,
0x3f54db31,0xbf0e39da,0x3f226799,0xbf45e403,0x3ec3ef15,0xbf6c835e,0x3dc8bd36,0xbf7ec46d,0xbe47c5c2,0xbf7b14be,0xbef15aea,0xbf61c598,
0x3f800000,0x0,0x3f710908,0xbeac7cd4,0x3f45e403,0xbf226799,0x3f039c3d,0xbf5b941a,0x3e47c5c2,0xbf7b14be,0xbe164083,0xbf7d3aac,
0xbef15aea,0xbf61c598,0xbf3daef9,0xbf2beb4a,0x3f800000,0x0,0x3f800000,0x0,0x3f800000,0x0,0x3f800000,0x0,
0x3f800000,0x0,0x3f800000,0x0,0x3f800000,0x0,0x3f800000,0x0,0x3f6c835e,0xbec3ef15,0x3f676bd8,0xbedae880,
0x3f61c598,0xbef15aea,0x3f5b941a,0xbf039c3d,0x3f54db31,0xbf0e39da,0x3f4d9f02,0xbf187fc0,0x3f45e403,0xbf226799,0x3f3daef9,0xbf2beb4a,
0x3f3504f3,0xbf3504f3,0x3f226799,0xbf45e403,0x3f0e39da,0xbf54db31,0x3ef15aea,0xbf61c598,0x3ec3ef15,0xbf6c835e,0x3e94a031,0xbf74fa0b,
0x3e47c5c2,0xbf7b14be,0x3dc8bd36,0xbf7ec46d,0x3ec3ef15,0xbf6c835e,0x3e78cfcc,0xbf7853f8,0x3dc8bd36,0xbf7ec46d,0xbd48fb30,0xbf7fb10f,
0xbe47c5c2,0xbf7b14be,0xbeac7cd4,0xbf710908,0xbef15aea,0xbf61c598,0xbf187fc0,0xbf4d9f02,0x0,0xbf800000,0xbe47c5c2,0xbf7b14be,
0xbec3ef15,0xbf6c835e,0xbf0e39da,0xbf54db31,0xbf3504f3,0xbf3504f3,0xbf54db31,0xbf0e39da,0xbf6c835e,0xbec3ef15,0xbf7b14be,0xbe47c5c2,
0xbec3ef15,0xbf6c835e,0xbf187fc0,0xbf4d9f02,0xbf45e403,0xbf226799,0xbf676bd8,0xbedae880,0xbf7b14be,0xbe47c5c2,0xbf7fb10f,0x3d48fb30,
0xbf74fa0b,0x3e94a031,0xbf5b941a,0x3f039c3d,0xbf3504f3,0xbf3504f3,0xbf61c598,0xbef15aea,0xbf7b14be,0xbe47c5c2,0xbf7ec46d,0x3dc8bd36,
0xbf6c835e,0x3ec3ef15,0xbf45e403,0x3f226799,0xbf0e39da,0x3f54db31,0xbe94a031,0x3f74fa0b,0xbf6c835e,0xbec3ef15,0xbf7fb10f,0xbd48fb30,
0xbf74fa0b,0x3e94a031,0xbf4d9f02,0x3f187fc0,0xbf0e39da,0x3f54db31,0xbe78cfcc,0x3f7853f8,0x3dc8bd36,0x3f7ec46d,0x3edae880,0x3f676bd8,
0x80003f80,0x3f800000,0x3f800000,0xbf80,0x3ec43f6d,0x3f6dbec4,0x3f6dbec4,0xbec4bf6d,0x3f353f35,0x3f35bf35,0x3f35bf35,0xbf35bf35,
0x3f6d3ec4,0x3ec4bf6d,0x3ec4bf6d,0xbf6dbec4,0x80003f80,0x3f800000,0xbf800000,0x3f80,0x3f6d3ec4,0x3ec4bf6d,0xbec43f6d,0x3f6d3ec4,
0x3f35bf35,0xbf35bf35,0x3f353f35,0x3f35bf35,0xbec4bf6d,0xbf6d3ec4,0x3f6dbec4,0xbec4bf6d,0x80003f80,0x3f800000,0x3f800000,0xbf80,
0x3f6dbec4,0xbec4bf6d,0xbec4bf6d,0xbf6d3ec4,0xbf35bf35,0xbf353f35,0xbf353f35,0x3f353f35,0xbec43f6d,0x3f6d3ec4,0x3f6d3ec4,0x3ec4bf6d,
0x80003f80,0x3f800000,0xbf800000,0x3f80,0x3ec4bf6d,0xbf6dbec4,0x3f6d3ec4,0x3ec4bf6d,0xbf353f35,0x3f353f35,0xbf35bf35,0xbf353f35,
0x3f6dbec4,0xbec4bf6d,0x3ec43f6d,0x3f6dbec4,0x80003f80,0x3f800000,0x3f800000,0xbf80,0xbec4bf6d,0xbf6d3ec4,0xbf6d3ec4,0x3ec43f6d,
0x3f353f35,0x3f35bf35,0x3f35bf35,0xbf35bf35,0xbf6dbec4,0xbec43f6d,0xbec43f6d,0x3f6d3ec4,0x80003f80,0x3f800000,0xbf800000,0x3f80,
0xbf6dbec4,0xbec43f6d,0x3ec4bf6d,0xbf6dbec4,0x3f35bf35,0xbf35bf35,0x3f353f35,0x3f35bf35,0x3ec43f6d,0x3f6dbec4,0xbf6d3ec4,0x3ec43f6d,
0x80003f80,0x3f800000,0x3f800000,0xbf80,0xbf6d3ec4,0x3ec43f6d,0x3ec43f6d,0x3f6dbec4,0xbf35bf35,0xbf353f35,0xbf353f35,0x3f353f35,
0x3ec4bf6d,0xbf6dbec4,0xbf6dbec4,0xbec43f6d,0x80003f80,0x3f800000,0xbf800000,0x3f80,0xbec43f6d,0x3f6d3ec4,0xbf6dbec4,0xbec43f6d,
0xbf353f35,0x3f353f35,0xbf35bf35,0xbf353f35,0xbf6d3ec4,0x3ec43f6d,0xbec4bf6d,0xbf6d3ec4,0x3f803f80,0x80008000,0x80008000,0xbf80bf80,
0x3f803f80,0x80008000,0x80008000,0xbf80bf80,0x3f803f80,0x80008000,0x80008000,0xbf80bf80,0x3f803f80,0x80008000,0x80008000,0xbf80bf80,
0x3ec43f6d,0x3f6d3ec4,0x3f6d3ec4,0xbec4bf6d,0xbf6dbec4,0x3ec43f6d,0x3ec43f6d,0x3f6d3ec4,0xbec4bf6d,0xbf6dbec4,0xbf6dbec4,0x3ec43f6d,
0x3f6d3ec4,0xbec4bf6d,0xbec4bf6d,0xbf6dbec4,0xbf353f35,0x3f353f35,0x3f353f35,0x3f35bf35,0x3f35bf35,0xbf35bf35,0xbf35bf35,0xbf353f35,
0xbf353f35,0x3f353f35,0x3f353f35,0x3f35bf35,0x3f35bf35,0xbf35bf35,0xbf35bf35,0xbf353f35,0xbf6d3ec4,0xbec43f6d,0xbec43f6d,0x3f6dbec4,
0xbec43f6d,0x3f6dbec4,0x3f6dbec4,0x3ec4bf6d,0x3f6dbec4,0x3ec4bf6d,0x3ec4bf6d,0xbf6d3ec4,0x3ec4bf6d,0xbf6d3ec4,0xbf6d3ec4,0xbec43f6d,
0x0,0xbf803f80,0xbf803f80,0x80008000,0x0,0xbf803f80,0xbf803f80,0x80008000,0x0,0xbf803f80,0xbf803f80,0x80008000,
0x0,0xbf803f80,0xbf803f80,0x80008000,0x3f6dbec4,0xbec43f6d,0xbec43f6d,0xbf6d3ec4,0x3ec4bf6d,0x3f6dbec4,0x3f6dbec4,0xbec43f6d,
0xbf6d3ec4,0x3ec4bf6d,0x3ec4bf6d,0x3f6dbec4,0xbec43f6d,0xbf6d3ec4,0xbf6d3ec4,0x3ec4bf6d,0x3f35bf35,0x3f353f35,0x3f353f35,0xbf353f35,
0xbf353f35,0xbf35bf35,0xbf35bf35,0x3f35bf35,0x3f35bf35,0x3f353f35,0x3f353f35,0xbf353f35,0xbf353f35,0xbf35bf35,0xbf35bf35,0x3f35bf35,
0xbec4bf6d,0x3f6d3ec4,0x3f6d3ec4,0x3ec43f6d,0x3f6d3ec4,0x3ec43f6d,0x3ec43f6d,0xbf6dbec4,0x3ec43f6d,0xbf6dbec4,0xbf6dbec4,0xbec4bf6d,
0xbf6dbec4,0xbec4bf6d,0xbec4bf6d,0x3f6d3ec4,0x3f800000,0x0,0x3f7fec43,0xbcc90ab0,0x3f7fb10f,0xbd48fb30,0x3f7f4e6d,0xbd96a905,
0x3f7ec46d,0xbdc8bd36,0x3f7e1324,0xbdfab273,0x3f7d3aac,0xbe164083,0x3f7c3b28,0xbe2f10a2,0x3f800000,0x0,0x3f7f4e6d,0xbd96a905,
0x3f7d3aac,0xbe164083,0x3f79c79d,0xbe605c13,0x3f74fa0b,0xbe94a031,0x3f6ed89e,0xbeb8442a,0x3f676bd8,0xbedae880,0x3f5ebe05,0xbefc5d27,
0x3f800000,0x0,0x3f7e1324,0xbdfab273,0x3f7853f8,0xbe78cfcc,0x3f6ed89e,0xbeb8442a,0x3f61c598,0xbef15aea,0x3f514d3d,0xbf13682a,
0x3f3daef9,0xbf2beb4a,0x3f273656,0xbf41d870,0x3f800000,0x0,0x3f7c3b28,0xbe2f10a2,0x3f710908,0xbeac7cd4,0x3f5ebe05,0xbefc5d27,
0x3f45e403,0xbf226799,0x3f273656,0xbf41d870,0x3f039c3d,0xbf5b941a,0x3eb8442a,0xbf6ed89e,0x3f800000,0x0,0x3f79c79d,0xbe605c13,
0x3f676bd8,0xbedae880,0x3f49d112,0xbf1d7fd1,0x3f226799,0xbf45e403,0x3ee63375,0xbf64aa59,0x3e78cfcc,0xbf7853f8,0x3cc90ab0,0xbf7fec43,
0x3f800000,0x0,0x3f76ba07,0xbe888e93,0x3f5b941a,0xbf039c3d,0x3f3085bb,0xbf396842,0x3ef15aea,0xbf61c598,0x3e605c13,0xbf79c79d,
0xbd48fb30,0xbf7fb10f,0xbea09ae5,0xbf731447,0x3f800000,0x0,0x3f731447,0xbea09ae5,0x3f4d9f02,0xbf187fc0,0x3f13682a,0xbf514d3d,
0x3e94a031,0xbf74fa0b,0xbcc90ab0,0xbf7fec43,0xbeac7cd4,0xbf710908,0xbf1d7fd1,0xbf49d112,0x3f800000,0x0,0x3f6ed89e,0xbeb8442a,
0x3f3daef9,0xbf2beb4a,0x3ee63375,0xbf64aa59,0x3dc8bd36,0xbf7ec46d,0xbe888e93,0xbf76ba07,0xbf187fc0,0xbf4d9f02,0xbf584853,0xbf08f59b,
0x3f7b14be,0xbe47c5c2,0x3f79c79d,0xbe605c13,0x3f7853f8,0xbe78cfcc,0x3f76ba07,0xbe888e93,0x3f74fa0b,0xbe94a031,0x3f731447,0xbea09ae5,
0x3f710908,0xbeac7cd4,0x3f6ed89e,0xbeb8442a,0x3f54db31,0xbf0e39da,0x3f49d112,0xbf1d7fd1,0x3f3daef9,0xbf2beb4a,0x3f3085bb,0xbf396842,
0x3f226799,0xbf45e403,0x3f13682a,0xbf514d3d,0x3f039c3d,0xbf5b941a,0x3ee63375,0xbf64aa59,0x3f0e39da,0xbf54db31,0x3ee63375,0xbf64aa59,
0x3eac7cd4,0xbf710908,0x3e605c13,0xbf79c79d,0x3dc8bd36,0xbf7ec46d,0xbcc90ab0,0xbf7fec43,0xbe164083,0xbf7d3aac,0xbe888e93,0xbf76ba07,
0x3e47c5c2,0xbf7b14be,0x3cc90ab0,0xbf7fec43,0xbe164083,0xbf7d3aac,0xbea09ae5,0xbf731447,0xbef15aea,0xbf61c598,0xbf1d7fd1,0xbf49d112,
0xbf3daef9,0xbf2beb4a,0xbf584853,0xbf08f59b,0xbe47c5c2,0xbf7b14be,0xbecf7bca,0xbf6a09a7,0xbf187fc0,0xbf4d9f02,0xbf41d870,0xbf273656,
0xbf61c598,0xbef15aea,0xbf76ba07,0xbe888e93,0xbf7fb10f,0xbd48fb30,0xbf7c3b28,0x3e2f10a2,0xbf0e39da,0xbf54db31,0xbf41d870,0xbf273656,
0xbf676bd8,0xbedae880,0xbf7c3b28,0xbe2f10a2,0xbf7ec46d,0x3dc8bd36,0xbf6ed89e,0x3eb8442a,0xbf4d9f02,0x3f187fc0,0xbf1d7fd1,0x3f49d112,
0xbf54db31,0xbf0e39da,0xbf76ba07,0xbe888e93,0xbf7fb10f,0x3d48fb30,0xbf6ed89e,0x3eb8442a,0xbf45e403,0x3f226799,0xbf08f59b,0x3f584853,
0xbe78cfcc,0x3f7853f8,0x3d96a905,0x3f7f4e6d,0xbf7b14be,0xbe47c5c2,0xbf7c3b28,0x3e2f10a2,0xbf5b941a,0x3f039c3d,0xbf1d7fd1,0x3f49d112,
0xbe94a031,0x3f74fa0b,0x3d96a905,0x3f7f4e6d,0x3edae880,0x3f676bd8,0x3f396842,0x3f3085bb,0x80003f80,0x80003f80,0x80003f80,0x80003f80,
0x80003f80,0x80003f80,0x80003f80,0x80003f80,0x80003f80,0x80003f80,0x80003f80,0x80003f80,0x80003f80,0x80003f80,0x80003f80,0x80003f80,
0x3f800000,0x3f800000,0x3f800000,0x3f800000,0x3f800000,0x3f800000,0x3f800000,0x3f800000,0x3f800000,0x3f800000,0x3f800000,0x3f800000,
0x3f800000,0x3f800000,0x3f800000,0x3f800000,0x80003f80,0x3f353f35,0x80003f80,0x3f353f35,0x3f800000,0x3f35bf35,0x3f800000,0x3f35bf35,
0x8000bf80,0xbf35bf35,0x8000bf80,0xbf35bf35,0xbf800000,0xbf353f35,0xbf800000,0xbf353f35,0x3f800000,0x3f35bf35,0x3f800000,0x3f35bf35,
0xbf80,0xbf35bf35,0xbf80,0xbf35bf35,0xbf800000,0xbf353f35,0xbf800000,0xbf353f35,0x3f80,0x3f353f35,0x3f80,0x3f353f35,
0x80003f80,0x3f800000,0x80003f80,0x3f800000,0x8000bf80,0xbf800000,0x8000bf80,0xbf800000,0x80003f80,0x3f800000,0x80003f80,0x3f800000,
0x8000bf80,0xbf800000,0x8000bf80,0xbf800000,0x3f800000,0xbf80,0x3f800000,0xbf80,0xbf800000,0x3f80,0xbf800000,0x3f80,
0x3f800000,0xbf80,0x3f800000,0xbf80,0xbf800000,0x3f80,0xbf800000,0x3f80,0x80003f80,0x3f35bf35,0x80003f80,0x3f35bf35,
0xbf800000,0x3f353f35,0xbf800000,0x3f353f35,0x8000bf80,0xbf353f35,0x8000bf80,0xbf353f35,0x3f800000,0xbf35bf35,0x3f800000,0xbf35bf35,
0x3f800000,0xbf35bf35,0x3f800000,0xbf35bf35,0x3f80,0x3f35bf35,0x3f80,0x3f35bf35,0xbf800000,0x3f353f35,0xbf800000,0x3f353f35,
0xbf80,0xbf353f35,0xbf80,0xbf353f35,0x80003f80,0x3ec43f6d,0x8000bf80,0xbec4bf6d,0x3f353f35,0x3f6d3ec4,0xbf35bf35,0xbf6dbec4,
0x3f800000,0x3f6dbec4,0xbf800000,0xbf6d3ec4,0x3f35bf35,0x3ec4bf6d,0xbf353f35,0xbec43f6d,0x3f800000,0x3f6dbec4,0xbf800000,0xbf6d3ec4,
0x3f35bf35,0x3ec4bf6d,0xbf353f35,0xbec43f6d,0xbf80,0xbec4bf6d,0x3f80,0x3ec43f6d,0xbf35bf35,0xbf6dbec4,0x3f353f35,0x3f6d3ec4,
0x80003f80,0x3f6d3ec4,0x8000bf80,0xbf6dbec4,0x3f35bf35,0xbec4bf6d,0xbf353f35,0x3ec43f6d,0xbf800000,0xbec43f6d,0x3f800000,0x3ec4bf6d,
0x3f353f35,0x3f6dbec4,0xbf35bf35,0xbf6d3ec4,0x3f800000,0x3ec4bf6d,0xbf800000,0xbec43f6d,0xbf35bf35,0xbf6d3ec4,0x3f353f35,0x3f6dbec4,
0x3f80,0x3f6d3ec4,0xbf80,0xbf6dbec4,0x3f35bf35,0xbec4bf6d,0xbf353f35,0x3ec43f6d,0x80003f80,0x3f6dbec4,0x8000bf80,0xbf6d3ec4,
0xbf35bf35,0xbec43f6d,0x3f353f35,0x3ec4bf6d,0x3f800000,0xbec4bf6d,0xbf800000,0x3ec43f6d,0xbf353f35,0x3f6d3ec4,0x3f35bf35,0xbf6dbec4,
0x3f800000,0xbec4bf6d,0xbf800000,0x3ec43f6d,0xbf353f35,0x3f6d3ec4,0x3f35bf35,0xbf6dbec4,0xbf80,0xbf6d3ec4,0x3f80,0x3f6dbec4,
0x3f353f35,0x3ec4bf6d,0xbf35bf35,0xbec43f6d,0x80003f80,0x3ec4bf6d,0x8000bf80,0xbec43f6d,0xbf353f35,0x3f6dbec4,0x3f35bf35,0xbf6d3ec4,
0xbf800000,0x3f6d3ec4,0x3f800000,0xbf6dbec4,0xbf35bf35,0x3ec43f6d,0x3f353f35,0xbec4bf6d,0x3f800000,0xbf6dbec4,0xbf800000,0x3f6d3ec4,
0x3f353f35,0xbec4bf6d,0xbf35bf35,0x3ec43f6d,0x3f80,0x3ec4bf6d,0xbf80,0xbec43f6d,0xbf353f35,0x3f6dbec4,0x3f35bf35,0xbf6d3ec4,
0x80003f80,0x8000bf80,0x80003f80,0x8000bf80,0x80003f80,0x8000bf80,0x80003f80,0x8000bf80,0x80003f80,0x8000bf80,0x80003f80,0x8000bf80,
0x80003f80,0x8000bf80,0x80003f80,0x8000bf80,0x3f800000,0xbf800000,0x3f800000,0xbf800000,0x3f800000,0xbf800000,0x3f800000,0xbf800000,
0x3f800000,0xbf800000,0x3f800000,0xbf800000,0x3f800000,0xbf800000,0x3f800000,0xbf800000,0x80003f80,0xbf35bf35,0x80003f80,0xbf35bf35,
0x3f800000,0xbf353f35,0x3f800000,0xbf353f35,0x8000bf80,0x3f353f35,0x8000bf80,0x3f353f35,0xbf800000,0x3f35bf35,0xbf800000,0x3f35bf35,
0x3f800000,0xbf353f35,0x3f800000,0xbf353f35,0xbf80,0x3f353f35,0xbf80,0x3f353f35,0xbf800000,0x3f35bf35,0xbf800000,0x3f35bf35,
0x3f80,0xbf35bf35,0x3f80,0xbf35bf35,0x80003f80,0xbf800000,0x80003f80,0xbf800000,0x8000bf80,0x3f800000,0x8000bf80,0x3f800000,
0x80003f80,0xbf800000,0x80003f80,0xbf800000,0x8000bf80,0x3f800000,0x8000bf80,0x3f800000,0x3f800000,0x3f80,0x3f800000,0x3f80,
0xbf800000,0xbf80,0xbf800000,0xbf80,0x3f800000,0x3f80,0x3f800000,0x3f80,0xbf800000,0xbf80,0xbf800000,0xbf80,
0x80003f80,0xbf353f35,0x80003f80,0xbf353f35,0xbf800000,0xbf35bf35,0xbf800000,0xbf35bf35,0x8000bf80,0x3f35bf35,0x8000bf80,0x3f35bf35,
0x3f800000,0x3f353f35,0x3f800000,0x3f353f35,0x3f800000,0x3f353f35,0x3f800000,0x3f353f35,0x3f80,0xbf353f35,0x3f80,0xbf353f35,
0xbf800000,0xbf35bf35,0xbf800000,0xbf35bf35,0xbf80,0x3f35bf35,0xbf80,0x3f35bf35,0x80003f80,0xbec4bf6d,0x8000bf80,0x3ec43f6d,
0x3f353f35,0xbf6dbec4,0xbf35bf35,0x3f6d3ec4,0x3f800000,0xbf6d3ec4,0xbf800000,0x3f6dbec4,0x3f35bf35,0xbec43f6d,0xbf353f35,0x3ec4bf6d,
0x3f800000,0xbf6d3ec4,0xbf800000,0x3f6dbec4,0x3f35bf35,0xbec43f6d,0xbf353f35,0x3ec4bf6d,0xbf80,0x3ec43f6d,0x3f80,0xbec4bf6d,
0xbf35bf35,0x3f6d3ec4,0x3f353f35,0xbf6dbec4,0x80003f80,0xbf6dbec4,0x8000bf80,0x3f6d3ec4,0x3f35bf35,0x3ec43f6d,0xbf353f35,0xbec4bf6d,
0xbf800000,0x3ec4bf6d,0x3f800000,0xbec43f6d,0x3f353f35,0xbf6d3ec4,0xbf35bf35,0x3f6dbec4,0x3f800000,0xbec43f6d,0xbf800000,0x3ec4bf6d,
0xbf35bf35,0x3f6dbec4,0x3f353f35,0xbf6d3ec4,0x3f80,0xbf6dbec4,0xbf80,0x3f6d3ec4,0x3f35bf35,0x3ec43f6d,0xbf353f35,0xbec4bf6d,
0x80003f80,0xbf6d3ec4,0x8000bf80,0x3f6dbec4,0xbf35bf35,0x3ec4bf6d,0x3f353f35,0xbec43f6d,0x3f800000,0x3ec43f6d,0xbf800000,0xbec4bf6d,
0xbf353f35,0xbf6dbec4,0x3f35bf35,0x3f6d3ec4,0x3f800000,0x3ec43f6d,0xbf800000,0xbec4bf6d,0xbf353f35,0xbf6dbec4,0x3f35bf35,0x3f6d3ec4,
0xbf80,0x3f6dbec4,0x3f80,0xbf6d3ec4,0x3f353f35,0xbec43f6d,0xbf35bf35,0x3ec4bf6d,0x80003f80,0xbec43f6d,0x8000bf80,0x3ec4bf6d,
0xbf353f35,0xbf6d3ec4,0x3f35bf35,0x3f6dbec4,0xbf800000,0xbf6dbec4,0x3f800000,0x3f6d3ec4,0xbf35bf35,0xbec4bf6d,0x3f353f35,0x3ec43f6d,
0x3f800000,0x3f6d3ec4,0xbf800000,0xbf6dbec4,0x3f353f35,0x3ec43f6d,0xbf35bf35,0xbec4bf6d,0x3f80,0xbec43f6d,0xbf80,0x3ec4bf6d,
0xbf353f35,0xbf6d3ec4,0x3f35bf35,0x3f6dbec4,
};
constexpr int TB_F = 0, TB_E = 512, TB_P2 = 1024;

enum { C_EP = 0, C_Z1 = 32, C_Z2 = 96, C_H3 = 128, C_U = 160, C_X = 256, C_TOTAL = 512 };
struct Scratch {
  unsigned cnt[C_TOTAL];
  uint32_t moda[8 * 2 * D_];
  uint32_t mod[4 * D_ + 256];
  uint32_t z1[120 * 5120];
  uint32_t z2[128 * 4800];
  uint32_t x1[S_ * D_ / 2];
  uint8_t h3[32 * 18 * 4096];
  uint8_t u[72 * D_ * 128];
  uint4 part[128 * 1152];
};
__device__ __align__(1024) Scratch g_s;

#define PF2 8
#define PF2K 16
#define HOLDA 5
#define GOAT 0
#define HW bulk_commit_wait
#define H3W 0
#define X1K 10
#define PEEK 1
#define H3G 1
#define PFF 2
#ifndef NV1
#define NV1 12
#endif
#ifndef NV2
#define NV2 20
#endif
#define GDEP 0
#define TRK0 50
#define W0N 3
#define TRKC 350
#define NG1 2

#define FAILCNT(k) do {} while (0)
#define CK(k) do {} while (0)
#define CKX(k) do {} while (0)
#define TS(k) do {} while (0)
#define TSC(k) do {} while (0)
struct Maps { CUtensorMap z1, z2[2], w1a, w1b, h3[2], w2, x1, out, wf[4], wm; };
struct Params {
  const __nv_bfloat16 *x, *c, *wmod;
  Scratch* s;
  const uint4* tab;
  const __nv_bfloat16 *wr, *wi, *w1, *w2, *b1, *b2;
};

__device__ __forceinline__ uint32_t smem_u32(const void* p) { return (uint32_t)__cvta_generic_to_shared(p); }
__device__ __forceinline__ void mbar_init(uint32_t b, int c) { asm volatile("mbarrier.init.shared::cta.b64 [%0], %1;" ::"r"(b), "r"(c)); }
__device__ __forceinline__ void mbar_expect(uint32_t b, int bytes) { asm volatile("mbarrier.arrive.expect_tx.shared::cta.b64 _, [%0], %1;" ::"r"(b), "r"(bytes) : "memory"); }
__device__ __forceinline__ void mbar_arrive(uint32_t b) { asm volatile("mbarrier.arrive.shared::cta.b64 _, [%0];" ::"r"(b) : "memory"); }
#define MBAR_WAIT(SEM)                                                                                                         \
  asm volatile("{\n.reg .pred p;\n.reg .u32 it;\nmov.u32 it, 0;\nW:\nmbarrier.try_wait.parity" SEM ".shared::cta.b64 p, [%0], %1;\n" \
               "@p bra.uni D;\nadd.u32 it, it, 1;\nsetp.lt.u32 p, it, 0x400000;\n@p bra.uni W;\ntrap;\nD:\n}" ::"r"(b), "r"(ph) : "memory")
__device__ __forceinline__ void mbar_wait(uint32_t b, int ph) { MBAR_WAIT(""); }
__device__ __forceinline__ uint32_t mbar_test(uint32_t b, int ph) {
  uint32_t ok;
  asm volatile("{\n.reg .pred p;\nmbarrier.test_wait.parity.shared::cta.b64 p, [%1], %2;\nselp.u32 %0, 1, 0, p;\n}\n" : "=r"(ok) : "r"(b), "r"(ph) : "memory");
  return ok;
}
__device__ __forceinline__ void tma2d(uint32_t dst, const CUtensorMap* m, int c0, int c1, uint32_t bar) {
  asm volatile("cp.async.bulk.tensor.2d.shared::cluster.global.mbarrier::complete_tx::bytes [%0], [%1, {%3, %4}], [%2];" ::"r"(dst), "l"(m), "r"(bar), "r"(c0), "r"(c1) : "memory");
}
__device__ __forceinline__ uint64_t pol_ef() { uint64_t p; asm("createpolicy.fractional.L2::evict_first.b64 %0, 1.0;" : "=l"(p)); return p; }
__device__ __forceinline__ void tma3d_ef(uint32_t dst, const CUtensorMap* m, int c1, int c2, uint32_t bar) {
  asm volatile("cp.async.bulk.tensor.3d.shared::cluster.global.mbarrier::complete_tx::bytes.L2::cache_hint [%0], [%1, {%3, %4, %5}], [%2], %6;" ::"r"(dst), "l"(m), "r"(bar), "r"(0), "r"(c1), "r"(c2), "l"(pol_ef()) : "memory");
}
__device__ __forceinline__ void tma4d_ef(uint32_t dst, const CUtensorMap* m, int c1, int c2, int c3, uint32_t bar) {
  asm volatile("cp.async.bulk.tensor.4d.shared::cluster.global.mbarrier::complete_tx::bytes.L2::cache_hint [%0], [%1, {%3, %7, %4, %5}], [%2], %6;" ::"r"(dst), "l"(m), "r"(bar), "r"(0), "r"(c2), "r"(c3), "l"(pol_ef()), "r"(c1) : "memory");
}
__device__ __forceinline__ void bulk_ld(uint32_t dst, const void* src, int bytes, uint32_t bar) {
  asm volatile("cp.async.bulk.shared::cluster.global.mbarrier::complete_tx::bytes [%0], [%1], %2, [%3];" ::"r"(dst), "l"(src), "r"(bytes), "r"(bar) : "memory");
}
__device__ __forceinline__ void bulk_st(void* dst, uint32_t src, int bytes) {
  asm volatile("cp.async.bulk.global.shared::cta.bulk_group [%0], [%1], %2;" ::"l"(dst), "r"(src), "r"(bytes) : "memory");
}
__device__ __forceinline__ void tma_st2d(const CUtensorMap* m, uint32_t src, int c0, int c1) {
  asm volatile("cp.async.bulk.tensor.2d.global.shared::cta.bulk_group [%0, {%2, %3}], [%1];" ::"l"(m), "r"(src), "r"(c0), "r"(c1) : "memory");
}
__device__ __forceinline__ void tma_st3d(const CUtensorMap* m, uint32_t src, int c0, int c1, int c2) {
  asm volatile("cp.async.bulk.tensor.3d.global.shared::cta.bulk_group [%0, {%2, %3, %4}], [%1];" ::"l"(m), "r"(src), "r"(c0), "r"(c1), "r"(c2) : "memory");
}
__device__ __forceinline__ void bulk_commit_wait_read() {
  asm volatile("cp.async.bulk.commit_group;" ::: "memory");
  asm volatile("cp.async.bulk.wait_group.read 0;" ::: "memory");
}
__device__ __forceinline__ void bulk_commit_wait() {
  asm volatile("cp.async.bulk.commit_group;" ::: "memory");
  asm volatile("cp.async.bulk.wait_group 0;" ::: "memory");
}
__device__ __forceinline__ void prefetch_l2(const void* p, int bytes) {
  asm volatile("cp.async.bulk.prefetch.L2.global [%0], %1;" ::"l"(p), "r"(bytes) : "memory");
}
__device__ __forceinline__ void wg_fence() { asm volatile("wgmma.fence.sync.aligned;" ::: "memory"); }
__device__ __forceinline__ void wg_commit() { asm volatile("wgmma.commit_group.sync.aligned;" ::: "memory"); }
template <int N> __device__ __forceinline__ void wg_wait() { asm volatile("wgmma.wait_group.sync.aligned %0;" ::"n"(N) : "memory"); }
template <int N> __device__ __forceinline__ void reg_fence(float (&d)[N]) {
#pragma unroll
  for (int i = 0; i < N; i++) asm volatile("" : "+f"(d[i])::"memory");
}
__device__ __forceinline__ void fence_async_smem() { asm volatile("fence.proxy.async.shared::cta;" ::: "memory"); }
__device__ __forceinline__ void fence_async_glb() { asm volatile("fence.proxy.async.global;" ::: "memory"); }
__device__ __forceinline__ uint32_t ld_rlx(const void* p) { uint32_t v; asm volatile("ld.relaxed.gpu.global.b32 %0, [%1];" : "=r"(v) : "l"(p) : "memory"); return v; }
__device__ __forceinline__ uint2 ld_rlx2(const void* p) { uint2 v; asm volatile("ld.relaxed.gpu.global.v2.b32 {%0,%1}, [%2];" : "=r"(v.x), "=r"(v.y) : "l"(p) : "memory"); return v; }
__device__ __forceinline__ uint4 ld_rlx4(const void* p) { uint4 v; asm volatile("ld.relaxed.gpu.global.v4.b32 {%0,%1,%2,%3}, [%4];" : "=r"(v.x), "=r"(v.y), "=r"(v.z), "=r"(v.w) : "l"(p) : "memory"); return v; }
__device__ __forceinline__ uint32_t ld_nc(const void* p) { uint32_t v; asm volatile("ld.global.nc.L1::no_allocate.b32 %0, [%1];" : "=r"(v) : "l"(p) : "memory"); return v; }
__device__ __forceinline__ uint4 ld_nc4(const void* p) { uint4 v; asm volatile("ld.global.nc.v4.b32 {%0,%1,%2,%3}, [%4];" : "=r"(v.x), "=r"(v.y), "=r"(v.z), "=r"(v.w) : "l"(p) : "memory"); return v; }
__device__ __forceinline__ uint32_t lds(uint32_t a) { uint32_t v; asm volatile("ld.shared.b32 %0, [%1];" : "=r"(v) : "r"(a) : "memory"); return v; }
__device__ __forceinline__ uint2 lds2(uint32_t a) { uint2 v; asm volatile("ld.shared.v2.b32 {%0,%1}, [%2];" : "=r"(v.x), "=r"(v.y) : "r"(a) : "memory"); return v; }
__device__ __forceinline__ uint4 lds4(uint32_t a) { uint4 v; asm volatile("ld.shared.v4.b32 {%0,%1,%2,%3}, [%4];" : "=r"(v.x), "=r"(v.y), "=r"(v.z), "=r"(v.w) : "r"(a) : "memory"); return v; }
__device__ __forceinline__ float lds_bf(uint32_t a) { uint32_t v; asm volatile("ld.shared.u16 %0, [%1];" : "=r"(v) : "r"(a) : "memory"); return __uint_as_float(v << 16); }
__device__ __forceinline__ void sts(uint32_t a, uint32_t v) { asm volatile("st.shared.b32 [%0], %1;" ::"r"(a), "r"(v) : "memory"); }
__device__ __forceinline__ void sts2(uint32_t a, uint32_t v0, uint32_t v1) { asm volatile("st.shared.v2.b32 [%0], {%1,%2};" ::"r"(a), "r"(v0), "r"(v1) : "memory"); }
__device__ __forceinline__ void sts4(uint32_t a, uint32_t v0, uint32_t v1, uint32_t v2, uint32_t v3) { asm volatile("st.shared.v4.b32 [%0], {%1,%2,%3,%4};" ::"r"(a), "r"(v0), "r"(v1), "r"(v2), "r"(v3) : "memory"); }
__device__ __forceinline__ void bar_sync(int id, int n) { asm volatile("bar.sync %0, %1;" ::"r"(id), "r"(n) : "memory"); }
__device__ __forceinline__ void bar_arrive(int id, int n) { asm volatile("bar.arrive %0, %1;" ::"r"(id), "r"(n) : "memory"); }
__device__ __forceinline__ void red_add(unsigned* p, unsigned v) { asm volatile("red.relaxed.gpu.global.add.u32 [%0], %1;" ::"l"(p), "r"(v) : "memory"); }
__device__ __forceinline__ bool any(bool p) { return __any_sync(0xffffffffu, p); }
__device__ __forceinline__ void pause(unsigned clks) {
  asm volatile("{\n.reg .pred p;\n.reg .u32 a, b;\nmov.u32 a, %%clock;\nW:\nmov.u32 b, %%clock;\nsub.u32 b, b, a;\nsetp.lt.s32 p, b, %0;\n@p bra.uni W;\n}" ::"r"(clks) : "memory");
}
constexpr int SPIN_MAX = 1 << 20;
__device__ __forceinline__ void wait_cnt(const unsigned* p, unsigned target) {
  int it = 0;
  while (any((int)(ld_rlx(p) - target) < 0) && ++it < SPIN_MAX) {}
}
__device__ __forceinline__ uint32_t pack_bf16(float lo, float hi) { uint32_t r; asm("cvt.rn.bf16x2.f32 %0, %1, %2;" : "=r"(r) : "f"(hi), "f"(lo)); return r; }
__device__ __forceinline__ float bf_lo(uint32_t v) { return __uint_as_float(v << 16); }
__device__ __forceinline__ float bf_hi(uint32_t v) { return __uint_as_float(v & 0xffff0000u); }
__device__ __forceinline__ uint32_t hadd2(uint32_t a, uint32_t b) { uint32_t r; asm("add.rn.bf16x2 %0, %1, %2;" : "=r"(r) : "r"(a), "r"(b)); return r; }
__device__ __forceinline__ uint32_t hmul2(uint32_t a, uint32_t b) { uint32_t r; asm("mul.rn.bf16x2 %0, %1, %2;" : "=r"(r) : "r"(a), "r"(b)); return r; }
__device__ __forceinline__ uint32_t hfma2(uint32_t a, uint32_t b, uint32_t c) { uint32_t r; asm("fma.rn.bf16x2 %0, %1, %2, %3;" : "=r"(r) : "r"(a), "r"(b), "r"(c)); return r; }
__device__ __forceinline__ float rbf(float x) { uint32_t r; asm("cvt.rn.bf16x2.f32 %0, %1, %2;" : "=r"(r) : "f"(x), "f"(0.0f)); return __uint_as_float(r); }
__device__ __forceinline__ void stmatrix4(uint32_t a, uint32_t r0, uint32_t r1, uint32_t r2, uint32_t r3) {
  asm volatile("stmatrix.sync.aligned.m8n8.x4.shared.b16 [%0], {%1,%2,%3,%4};" ::"r"(a), "r"(r0), "r"(r1), "r"(r2), "r"(r3) : "memory");
}
__device__ __forceinline__ void stmatrix2(uint32_t a, uint32_t r0, uint32_t r1) {
  asm volatile("stmatrix.sync.aligned.m8n8.x2.shared.b16 [%0], {%1,%2};" ::"r"(a), "r"(r0), "r"(r1) : "memory");
}
__device__ __forceinline__ void stmatrix4t(uint32_t a, uint32_t r0, uint32_t r1, uint32_t r2, uint32_t r3) {
  asm volatile("stmatrix.sync.aligned.m8n8.x4.trans.shared.b16 [%0], {%1,%2,%3,%4};" ::"r"(a), "r"(r0), "r"(r1), "r"(r2), "r"(r3) : "memory");
}
__device__ __forceinline__ uint32_t movm(uint32_t a) { uint32_t r; asm("movmatrix.sync.aligned.m8n8.trans.b16 %0, %1;" : "=r"(r) : "r"(a)); return r; }
template <bool ACC> __device__ __forceinline__ void mma16(float* d, uint32_t a0, uint32_t a1, uint32_t a2, uint32_t a3, uint32_t b0, uint32_t b1) {
  if (ACC) asm("mma.sync.aligned.m16n8k16.row.col.f32.bf16.bf16.f32 {%0,%1,%2,%3}, {%4,%5,%6,%7}, {%8,%9}, {%0,%1,%2,%3};"
               : "+f"(d[0]), "+f"(d[1]), "+f"(d[2]), "+f"(d[3]) : "r"(a0), "r"(a1), "r"(a2), "r"(a3), "r"(b0), "r"(b1));
  else asm("mma.sync.aligned.m16n8k16.row.col.f32.bf16.bf16.f32 {%0,%1,%2,%3}, {%4,%5,%6,%7}, {%8,%9}, {%10,%10,%10,%10};"
           : "=f"(d[0]), "=f"(d[1]), "=f"(d[2]), "=f"(d[3]) : "r"(a0), "r"(a1), "r"(a2), "r"(a3), "r"(b0), "r"(b1), "f"(0.f));
}
__device__ __forceinline__ uint32_t pin(uint32_t v) { uint32_t r; asm volatile("shfl.sync.bfly.b32 %0, %1, 0, 31, 0xffffffff;" : "=r"(r) : "r"(v)); return r; }
template <class T> __device__ __forceinline__ T* pin(T* p) {
  const uint64_t a = reinterpret_cast<uint64_t>(p);
  return reinterpret_cast<T*>((uint64_t)pin((uint32_t)a) | ((uint64_t)pin((uint32_t)(a >> 32)) << 32));
}
__device__ __forceinline__ uint32_t upin(uint32_t v) { return __shfl_sync(0xffffffffu, v, 0); }
template <class T> __device__ __forceinline__ T* upin(T* p) {
  const uint64_t a = reinterpret_cast<uint64_t>(p);
  return reinterpret_cast<T*>((uint64_t)upin((uint32_t)a) | ((uint64_t)upin((uint32_t)(a >> 32)) << 32));
}
__device__ __forceinline__ bool elect() {
  uint32_t p;
  asm volatile("{\n.reg .pred P;\nelect.sync _|P, 0xffffffff;\nselp.u32 %0, 1, 0, P;\n}" : "=r"(p));
  return p;
}
__device__ __forceinline__ uint32_t set_tag(uint32_t w, uint32_t tag) { uint32_t r; asm("lop3.b32 %0, %1, 0xfffffffe, %2, 0xea;" : "=r"(r) : "r"(w), "r"(tag)); return r; }
__device__ __forceinline__ uint32_t and_or(uint32_t w, uint32_t a, uint32_t o) { uint32_t r; asm("lop3.b32 %0, %1, %2, %3, 0xea;" : "=r"(r) : "r"(w), "r"(a), "r"(o)); return r; }
__device__ __forceinline__ uint32_t or3(uint32_t a, uint32_t b, uint32_t c) { uint32_t r; asm("lop3.b32 %0, %1, %2, %3, 0xfe;" : "=r"(r) : "r"(a), "r"(b), "r"(c)); return r; }
__device__ __forceinline__ uint32_t diff2(uint32_t a, uint32_t b, uint32_t tag) { uint32_t r; asm("lop3.b32 %0, %1, %2, %3, 0x7e;" : "=r"(r) : "r"(a), "r"(b), "r"(tag)); return r; }
__device__ __forceinline__ float2 cmul(float2 a, float2 b) { return make_float2(a.x * b.x - a.y * b.y, a.x * b.y + a.y * b.x); }

template<int TB> __device__ __forceinline__ void wgmma_ss_160_0(float (&d)[96], uint32_t al, uint32_t ah, uint32_t bl, uint32_t bh) {
  asm volatile("{\n.reg .b64 da, db;\nmov.b64 da, {%80, %81};\nmov.b64 db, {%82, %83};\n"
    "wgmma.mma_async.sync.aligned.m64n160k16.f32.bf16.bf16 {%0,%1,%2,%3,%4,%5,%6,%7,%8,%9,%10,%11,%12,%13,%14,%15,%16,%17,%18,%19,%20,%21,%22,%23,%24,%25,%26,%27,%28,%29,%30,%31,%32,%33,%34,%35,%36,%37,%38,%39,%40,%41,%42,%43,%44,%45,%46,%47,%48,%49,%50,%51,%52,%53,%54,%55,%56,%57,%58,%59,%60,%61,%62,%63,%64,%65,%66,%67,%68,%69,%70,%71,%72,%73,%74,%75,%76,%77,%78,%79}, da, db, 1, 1, 1, 1, %84;\n}\n"
    : "+f"(d[0]),"+f"(d[1]),"+f"(d[2]),"+f"(d[3]),"+f"(d[4]),"+f"(d[5]),"+f"(d[6]),"+f"(d[7]),"+f"(d[8]),"+f"(d[9]),"+f"(d[10]),"+f"(d[11]),"+f"(d[12]),"+f"(d[13]),"+f"(d[14]),"+f"(d[15]),"+f"(d[16]),"+f"(d[17]),"+f"(d[18]),"+f"(d[19]),"+f"(d[20]),"+f"(d[21]),"+f"(d[22]),"+f"(d[23]),"+f"(d[24]),"+f"(d[25]),"+f"(d[26]),"+f"(d[27]),"+f"(d[28]),"+f"(d[29]),"+f"(d[30]),"+f"(d[31]),"+f"(d[32]),"+f"(d[33]),"+f"(d[34]),"+f"(d[35]),"+f"(d[36]),"+f"(d[37]),"+f"(d[38]),"+f"(d[39]),"+f"(d[40]),"+f"(d[41]),"+f"(d[42]),"+f"(d[43]),"+f"(d[44]),"+f"(d[45]),"+f"(d[46]),"+f"(d[47]),"+f"(d[48]),"+f"(d[49]),"+f"(d[50]),"+f"(d[51]),"+f"(d[52]),"+f"(d[53]),"+f"(d[54]),"+f"(d[55]),"+f"(d[56]),"+f"(d[57]),"+f"(d[58]),"+f"(d[59]),"+f"(d[60]),"+f"(d[61]),"+f"(d[62]),"+f"(d[63]),"+f"(d[64]),"+f"(d[65]),"+f"(d[66]),"+f"(d[67]),"+f"(d[68]),"+f"(d[69]),"+f"(d[70]),"+f"(d[71]),"+f"(d[72]),"+f"(d[73]),"+f"(d[74]),"+f"(d[75]),"+f"(d[76]),"+f"(d[77]),"+f"(d[78]),"+f"(d[79])
    : "r"(al), "r"(ah), "r"(bl), "r"(bh), "n"(TB));
}
template<int TB> __device__ __forceinline__ void wgmma_ss_144_0(float (&d)[96], uint32_t al, uint32_t ah, uint32_t bl, uint32_t bh) {
  asm volatile("{\n.reg .b64 da, db;\nmov.b64 da, {%72, %73};\nmov.b64 db, {%74, %75};\n"
    "wgmma.mma_async.sync.aligned.m64n144k16.f32.bf16.bf16 {%0,%1,%2,%3,%4,%5,%6,%7,%8,%9,%10,%11,%12,%13,%14,%15,%16,%17,%18,%19,%20,%21,%22,%23,%24,%25,%26,%27,%28,%29,%30,%31,%32,%33,%34,%35,%36,%37,%38,%39,%40,%41,%42,%43,%44,%45,%46,%47,%48,%49,%50,%51,%52,%53,%54,%55,%56,%57,%58,%59,%60,%61,%62,%63,%64,%65,%66,%67,%68,%69,%70,%71}, da, db, 1, 1, 1, 1, %76;\n}\n"
    : "+f"(d[0]),"+f"(d[1]),"+f"(d[2]),"+f"(d[3]),"+f"(d[4]),"+f"(d[5]),"+f"(d[6]),"+f"(d[7]),"+f"(d[8]),"+f"(d[9]),"+f"(d[10]),"+f"(d[11]),"+f"(d[12]),"+f"(d[13]),"+f"(d[14]),"+f"(d[15]),"+f"(d[16]),"+f"(d[17]),"+f"(d[18]),"+f"(d[19]),"+f"(d[20]),"+f"(d[21]),"+f"(d[22]),"+f"(d[23]),"+f"(d[24]),"+f"(d[25]),"+f"(d[26]),"+f"(d[27]),"+f"(d[28]),"+f"(d[29]),"+f"(d[30]),"+f"(d[31]),"+f"(d[32]),"+f"(d[33]),"+f"(d[34]),"+f"(d[35]),"+f"(d[36]),"+f"(d[37]),"+f"(d[38]),"+f"(d[39]),"+f"(d[40]),"+f"(d[41]),"+f"(d[42]),"+f"(d[43]),"+f"(d[44]),"+f"(d[45]),"+f"(d[46]),"+f"(d[47]),"+f"(d[48]),"+f"(d[49]),"+f"(d[50]),"+f"(d[51]),"+f"(d[52]),"+f"(d[53]),"+f"(d[54]),"+f"(d[55]),"+f"(d[56]),"+f"(d[57]),"+f"(d[58]),"+f"(d[59]),"+f"(d[60]),"+f"(d[61]),"+f"(d[62]),"+f"(d[63]),"+f"(d[64]),"+f"(d[65]),"+f"(d[66]),"+f"(d[67]),"+f"(d[68]),"+f"(d[69]),"+f"(d[70]),"+f"(d[71])
    : "r"(al), "r"(ah), "r"(bl), "r"(bh), "n"(TB));
}
template<int TB> __device__ __forceinline__ void wgmma_ss_96_0(float (&d)[96], uint32_t al, uint32_t ah, uint32_t bl, uint32_t bh) {
  asm volatile("{\n.reg .b64 da, db;\nmov.b64 da, {%48, %49};\nmov.b64 db, {%50, %51};\n"
    "wgmma.mma_async.sync.aligned.m64n96k16.f32.bf16.bf16 {%0,%1,%2,%3,%4,%5,%6,%7,%8,%9,%10,%11,%12,%13,%14,%15,%16,%17,%18,%19,%20,%21,%22,%23,%24,%25,%26,%27,%28,%29,%30,%31,%32,%33,%34,%35,%36,%37,%38,%39,%40,%41,%42,%43,%44,%45,%46,%47}, da, db, 1, 1, 1, 1, %52;\n}\n"
    : "+f"(d[0]),"+f"(d[1]),"+f"(d[2]),"+f"(d[3]),"+f"(d[4]),"+f"(d[5]),"+f"(d[6]),"+f"(d[7]),"+f"(d[8]),"+f"(d[9]),"+f"(d[10]),"+f"(d[11]),"+f"(d[12]),"+f"(d[13]),"+f"(d[14]),"+f"(d[15]),"+f"(d[16]),"+f"(d[17]),"+f"(d[18]),"+f"(d[19]),"+f"(d[20]),"+f"(d[21]),"+f"(d[22]),"+f"(d[23]),"+f"(d[24]),"+f"(d[25]),"+f"(d[26]),"+f"(d[27]),"+f"(d[28]),"+f"(d[29]),"+f"(d[30]),"+f"(d[31]),"+f"(d[32]),"+f"(d[33]),"+f"(d[34]),"+f"(d[35]),"+f"(d[36]),"+f"(d[37]),"+f"(d[38]),"+f"(d[39]),"+f"(d[40]),"+f"(d[41]),"+f"(d[42]),"+f"(d[43]),"+f"(d[44]),"+f"(d[45]),"+f"(d[46]),"+f"(d[47])
    : "r"(al), "r"(ah), "r"(bl), "r"(bh), "n"(TB));
}
template<int TB> __device__ __forceinline__ void wgmma_ss_96_48(float (&d)[96], uint32_t al, uint32_t ah, uint32_t bl, uint32_t bh) {
  asm volatile("{\n.reg .b64 da, db;\nmov.b64 da, {%48, %49};\nmov.b64 db, {%50, %51};\n"
    "wgmma.mma_async.sync.aligned.m64n96k16.f32.bf16.bf16 {%0,%1,%2,%3,%4,%5,%6,%7,%8,%9,%10,%11,%12,%13,%14,%15,%16,%17,%18,%19,%20,%21,%22,%23,%24,%25,%26,%27,%28,%29,%30,%31,%32,%33,%34,%35,%36,%37,%38,%39,%40,%41,%42,%43,%44,%45,%46,%47}, da, db, 1, 1, 1, 1, %52;\n}\n"
    : "+f"(d[48]),"+f"(d[49]),"+f"(d[50]),"+f"(d[51]),"+f"(d[52]),"+f"(d[53]),"+f"(d[54]),"+f"(d[55]),"+f"(d[56]),"+f"(d[57]),"+f"(d[58]),"+f"(d[59]),"+f"(d[60]),"+f"(d[61]),"+f"(d[62]),"+f"(d[63]),"+f"(d[64]),"+f"(d[65]),"+f"(d[66]),"+f"(d[67]),"+f"(d[68]),"+f"(d[69]),"+f"(d[70]),"+f"(d[71]),"+f"(d[72]),"+f"(d[73]),"+f"(d[74]),"+f"(d[75]),"+f"(d[76]),"+f"(d[77]),"+f"(d[78]),"+f"(d[79]),"+f"(d[80]),"+f"(d[81]),"+f"(d[82]),"+f"(d[83]),"+f"(d[84]),"+f"(d[85]),"+f"(d[86]),"+f"(d[87]),"+f"(d[88]),"+f"(d[89]),"+f"(d[90]),"+f"(d[91]),"+f"(d[92]),"+f"(d[93]),"+f"(d[94]),"+f"(d[95])
    : "r"(al), "r"(ah), "r"(bl), "r"(bh), "n"(TB));
}
__device__ __forceinline__ void wgmma_rs_72(float (&d)[36], uint32_t a0, uint32_t a1, uint32_t a2, uint32_t a3, uint32_t bl, uint32_t bh, int sd) {
  asm volatile("{\n.reg .pred p;\n.reg .b64 db;\nsetp.ne.b32 p, %42, 0;\nmov.b64 db, {%40, %41};\n"
    "wgmma.mma_async.sync.aligned.m64n72k16.f32.bf16.bf16 {%0,%1,%2,%3,%4,%5,%6,%7,%8,%9,%10,%11,%12,%13,%14,%15,%16,%17,%18,%19,%20,%21,%22,%23,%24,%25,%26,%27,%28,%29,%30,%31,%32,%33,%34,%35}, {%36,%37,%38,%39}, db, p, 1, 1, 1;\n}\n"
    : "+f"(d[0]),"+f"(d[1]),"+f"(d[2]),"+f"(d[3]),"+f"(d[4]),"+f"(d[5]),"+f"(d[6]),"+f"(d[7]),"+f"(d[8]),"+f"(d[9]),"+f"(d[10]),"+f"(d[11]),"+f"(d[12]),"+f"(d[13]),"+f"(d[14]),"+f"(d[15]),"+f"(d[16]),"+f"(d[17]),"+f"(d[18]),"+f"(d[19]),"+f"(d[20]),"+f"(d[21]),"+f"(d[22]),"+f"(d[23]),"+f"(d[24]),"+f"(d[25]),"+f"(d[26]),"+f"(d[27]),"+f"(d[28]),"+f"(d[29]),"+f"(d[30]),"+f"(d[31]),"+f"(d[32]),"+f"(d[33]),"+f"(d[34]),"+f"(d[35])
    : "r"(a0), "r"(a1), "r"(a2), "r"(a3), "r"(bl), "r"(bh), "r"(sd));
}
__device__ __forceinline__ void wgmma_rs_48(float (&d)[24], uint32_t a0, uint32_t a1, uint32_t a2, uint32_t a3, uint32_t bl, uint32_t bh, int sd) {
  asm volatile("{\n.reg .pred p;\n.reg .b64 db;\nsetp.ne.b32 p, %30, 0;\nmov.b64 db, {%28, %29};\n"
    "wgmma.mma_async.sync.aligned.m64n48k16.f32.bf16.bf16 {%0,%1,%2,%3,%4,%5,%6,%7,%8,%9,%10,%11,%12,%13,%14,%15,%16,%17,%18,%19,%20,%21,%22,%23}, {%24,%25,%26,%27}, db, p, 1, 1, 1;\n}\n"
    : "+f"(d[0]),"+f"(d[1]),"+f"(d[2]),"+f"(d[3]),"+f"(d[4]),"+f"(d[5]),"+f"(d[6]),"+f"(d[7]),"+f"(d[8]),"+f"(d[9]),"+f"(d[10]),"+f"(d[11]),"+f"(d[12]),"+f"(d[13]),"+f"(d[14]),"+f"(d[15]),"+f"(d[16]),"+f"(d[17]),"+f"(d[18]),"+f"(d[19]),"+f"(d[20]),"+f"(d[21]),"+f"(d[22]),"+f"(d[23])
    : "r"(a0), "r"(a1), "r"(a2), "r"(a3), "r"(bl), "r"(bh), "r"(sd));
}
template<int N,int OFF,int TB> __device__ __forceinline__ void wgmma_ss(float (&d)[96], uint32_t al, uint32_t ah, uint32_t bl, uint32_t bh) {
  if constexpr (N==160 && OFF==0) wgmma_ss_160_0<TB>(d, al, ah, bl, bh);
  else if constexpr (N==144 && OFF==0) wgmma_ss_144_0<TB>(d, al, ah, bl, bh);
  else if constexpr (N==96 && OFF==0) wgmma_ss_96_0<TB>(d, al, ah, bl, bh);
  else if constexpr (N==96 && OFF==48) wgmma_ss_96_48<TB>(d, al, ah, bl, bh);
}

__device__ __forceinline__ void dft3(float2& a, float2& b, float2& c) {
  const float s = 0.86602540378443864676f;
  float2 t = make_float2(b.x + c.x, b.y + c.y), d = make_float2(b.x - c.x, b.y - c.y);
  float2 m = make_float2(fmaf(-0.5f, t.x, a.x), fmaf(-0.5f, t.y, a.y));
  a = make_float2(a.x + t.x, a.y + t.y);
  b = make_float2(fmaf(s, d.y, m.x), fmaf(-s, d.x, m.y));
  c = make_float2(fmaf(-s, d.y, m.x), fmaf(s, d.x, m.y));
}
__device__ __forceinline__ void dft9(float2 (&x)[9]) {
  const float2 w1 = make_float2(0.76604444311897803520f, -0.64278760968653932632f);
  const float2 w2 = make_float2(0.17364817766693034885f, -0.98480775301220805937f);
  const float2 w4 = make_float2(-0.93969262078590838405f, -0.34202014332566873304f);
  dft3(x[0], x[3], x[6]); dft3(x[1], x[4], x[7]); dft3(x[2], x[5], x[8]);
  x[4] = cmul(x[4], w1); x[7] = cmul(x[7], w2); x[5] = cmul(x[5], w2); x[8] = cmul(x[8], w4);
  dft3(x[0], x[1], x[2]); dft3(x[3], x[4], x[5]); dft3(x[6], x[7], x[8]);
  float2 t;
  t = x[1]; x[1] = x[3]; x[3] = t;
  t = x[2]; x[2] = x[6]; x[6] = t;
  t = x[5]; x[5] = x[7]; x[7] = t;
}

__device__ __forceinline__ uint32_t* mod_ptr(Scratch* sc, int u, int t128) {
  const int i = t128 & 15;
  return u < 72 ? sc->moda + (t128 >> 4) * (2 * D_) + 16 * u + 2 * (i & 7) + (i >> 3) : sc->mod + 16 * (u - 72) + i;
}
__device__ __forceinline__ void mod_unit(Scratch* sc, int u, int t128, uint32_t sw_, uint32_t bar, int ph, uint32_t rb, uint32_t tag) {
  const int w = t128 >> 5, l = t128 & 31;
  uint32_t b[18];
#pragma unroll
  for (int i = 0; i < 18; i++) b[i] = lds(red + 512 + (72 * w + 4 * i + (l & 3)) * 4);
  const uint32_t sa = pin(sw_ + (144 * w + (l & 7) + 8 * (l >> 4)) * 32 + (((l >> 3) ^ (l >> 2)) & 1) * 16);
  const uint32_t sr = pin(rb + (l >> 2) * 16 + w * 4);
  uint32_t* const dst = pin(mod_ptr(sc, u, t128));
  const int kind = u / 36;
  const float mul = __uint_as_float(pin(__float_as_uint(kind == 0 ? 16.0f : 1.0f))), add = __uint_as_float(pin(__float_as_uint(kind == 1 || kind == 4 ? 1.0f : 0.0f)));
  mbar_wait(bar, ph);
  if (t128 == 0 && u < 72) TS(10);
  float d[3][4];
#pragma unroll
  for (int i = 0; i < 9; i++) {
    uint32_t a0, a1, a2, a3;
    asm volatile("ldmatrix.sync.aligned.m8n8.x4.trans.shared.b16 {%0,%1,%2,%3}, [%4];" : "=r"(a0), "=r"(a1), "=r"(a2), "=r"(a3) : "r"(sa + i * 512) : "memory");
    if (i < 3) mma16<false>(d[i], a0, a1, a2, a3, b[2 * i], b[2 * i + 1]);
    else mma16<true>(d[i % 3], a0, a1, a2, a3, b[2 * i], b[2 * i + 1]);
  }
  if ((l & 3) == 0) { sts(sr, __float_as_uint(d[0][0] + d[1][0] + d[2][0])); sts(sr + 128, __float_as_uint(d[0][2] + d[1][2] + d[2][2])); }
  bar_sync(4, 128);
  const uint4 v = lds4(rb + (l & 15) * 16);
  const float m = rbf(fmaf(rbf((__uint_as_float(v.x) + __uint_as_float(v.y)) + (__uint_as_float(v.z) + __uint_as_float(v.w))), mul, add));
  if (u < 72 || t128 < 16) *dst = __float_as_uint(m) | tag;
}

__device__ __forceinline__ float rsq(float x) { float r; asm("rsqrt.approx.ftz.f32 %0, %1;" : "=f"(r) : "f"(x)); return r; }
__device__ __forceinline__ void ln_stats2(const float (&a)[18], const float (&b)[18], float sc, float& oa, float& ra, float& ob, float& rb) {
  float v[4] = {0.f, 0.f, 0.f, 0.f}, w[4] = {0.f, 0.f, 0.f, 0.f};
#pragma unroll
  for (int i = 0; i < 18; i += 2) {
    v[0] += a[i]; v[1] = fmaf(a[i], a[i], v[1]); v[2] += b[i]; v[3] = fmaf(b[i], b[i], v[3]);
    w[0] += a[i + 1]; w[1] = fmaf(a[i + 1], a[i + 1], w[1]); w[2] += b[i + 1]; w[3] = fmaf(b[i + 1], b[i + 1], w[3]);
  }
#pragma unroll
  for (int e = 0; e < 4; e++) v[e] += w[e];
#pragma unroll
  for (int o = 16; o; o >>= 1) {
#pragma unroll
    for (int e = 0; e < 4; e++) v[e] += __shfl_xor_sync(0xffffffffu, v[e], o);
  }
  const float ma = v[0] * (1.0f / D_), mb = v[2] * (1.0f / D_);
  ra = sc * rsq(fmaxf(fmaf(-ma, ma, v[1] * (1.0f / D_)), 0.f) + 1e-5f);
  rb = sc * rsq(fmaxf(fmaf(-mb, mb, v[3] * (1.0f / D_)), 0.f) + 1e-5f);
  oa = -ma * ra; ob = -mb * rb;
}

__device__ __forceinline__ float tmat(int c, int q, int j) {
  const int ph = q == 1 ? 1024 * j : (q >> 1) * (c + 128 * j) + 512 * (q & 1);
  return __cosf((float)(((ph + 1024) & 2047) - 1024) * (6.283185307179586f / 2048.0f));
}
__device__ __forceinline__ uint32_t line_off(int k1, int kap, int pi, int f) {
  int kd = 64 * k1 + 9 * kap;
  if (kap == 0 && k1 > 4) kd -= 288;
  if (kd >= D_) kd -= D_;
  return pi * 2400 + ((min(kd, D_ - kd) ^ f) << 3);
}

constexpr int JSK = 5;
struct Ring { uint32_t st, ph; };
template <bool G2, class T> __device__ __forceinline__ void ring_next(T& st, T& ph) {
  if (++st == NST) st = 0;
  ph ^= ((G2 ? 0xDu : 0x1u) >> st) & 1;
}
__device__ __forceinline__ void arrive_if(uint32_t a, uint32_t p) {
  asm volatile("{\n.reg .pred p;\nsetp.ne.u32 p, %1, 0;\n@p mbarrier.arrive.shared::cta.b64 _, [%0];\n}" ::"r"(a), "r"(p) : "memory");
}
template <int NA> __device__ __forceinline__ void reg_fence_n(float (&d)[96]) {
#pragma unroll
  for (int i = 0; i < NA; i++) asm volatile("" : "+f"(d[i])::"memory");
}
template <int MODE>
__device__ __forceinline__ void gemm_main(float (&acc)[96], uint32_t da0, uint32_t da1, uint32_t db0, int wg, Ring& rg,
                                          uint32_t* x1p, const uint32_t (&xr)[18]) {
  static_assert(JSK == NST - 1, "the held slot is the first one that is not refilled by GEMM1");
  constexpr int NKB = MODE == 3 ? 36 : 32;
  constexpr uint32_t HA = 0x40000040u, HB = MODE == 3 ? 0x40000040u : 0x80000020u;
  constexpr uint32_t KA = 2048 >> 4, KB = MODE == 3 ? (32 >> 4) : (1024 >> 4);
  constexpr int NA = MODE == 3 ? 72 : MODE == 1 ? 96 : 80;
  const uint32_t t = threadIdx.x & 127;
  const uint32_t eb = full0 + 8 * NST;
  uint32_t pb = 0, rel = t == 0, prel = 0, ok = 0;
  int n = MODE == 3 ? NKB - JSK : X1K + 2 * wg;
#pragma unroll 1
  for (int pass = MODE == 3 ? 0 : -1;; pass++) {
#pragma unroll 1
    do {
      const uint32_t so = rg.st * ((MODE == 3 ? STAGE2 : STAGE) >> 4), cb = eb + 8 * rg.st;
      if (__builtin_expect(!ok, 0)) mbar_wait(full0 + 8 * rg.st, rg.ph);
      reg_fence_n<NA>(acc);
      if (MODE == 1 && wg) {
        wg_fence();
#pragma unroll
        for (int k = 0; k < 4; k++) wgmma_ss<96, 48, 1>(acc, da1 + so + k * KA, HA, db0 + so + k * KB, HB);
        wg_commit();
      }
      wg_fence();
#pragma unroll
      for (int k = 0; k < 4; k++) {
        if (k == 3) { ring_next<MODE == 3>(rg.st, rg.ph); ok = PEEK ? mbar_test(full0 + 8 * rg.st, rg.ph) : 0; }
        if (MODE == 0) wgmma_ss<160, 0, 1>(acc, da0 + so + k * KA, HA, db0 + so + k * KB, HB);
        else if (MODE == 3) wgmma_ss<144, 0, 0>(acc, da0 + so + k * KA, HA, db0 + so + k * KB, HB);
        else wgmma_ss<96, 0, 1>(acc, da0 + so + k * KA, HA, db0 + so + k * KB, HB);
      }
      wg_commit();
      wg_wait<1>();
      reg_fence_n<NA>(acc);
      arrive_if(pb, prel);
      pb = cb; prel = rel;
    } while (--n);
    if (pass == 2 - wg) break;
    if (MODE != 3 && pass < 0) {
      if (blockIdx.x < 128) {
#pragma unroll
        for (int i = 0; i < 9; i++) { x1p[32 * i] = xr[i]; x1p[128 * 288 + 32 * i] = xr[9 + i]; }
      }
      n = NKB - JSK - X1K - 2 * wg;
      continue;
    }
    n = 1;
    if (pass == 0) {
      if (MODE != 3) prel = rel & wg;
      else rel = 0;
      n = JSK - 1 + wg;
      if (!wg) continue;
      wg_wait<0>();
      arrive_if(pb, prel);
      prel = 0;
    }
    bar_sync(1, 256);
  }
  wg_wait<0>();
  reg_fence_n<NA>(acc);
  if (MODE != 3) arrive_if(pb, MODE == 1 ? prel & ~wg : prel);
}

constexpr float GK1 = 2.0f * 0.7978845608028654f, GK3 = 8.0f * 0.044715f * 0.7978845608028654f;

__device__ __forceinline__ int kb2_order(int i) { const int wv = i / 6; return 6 * (i - 6 * wv) + ((0x431250 >> (4 * wv)) & 7); }

__device__ __forceinline__ void wait_flags(const unsigned* base, int n, int idx, unsigned target, uint64_t& ready) {
  if ((ready >> idx) & 1) return;
  const int l = threadIdx.x & 31;
  int it = 0;
  while (true) {
    unsigned a = ld_rlx(base + l), b = l + 32 < n ? ld_rlx(base + l + 32) : target;
    ready = (uint64_t)__ballot_sync(0xffffffffu, (int)(a - target) >= 0) | ((uint64_t)__ballot_sync(0xffffffffu, (int)(b - target) >= 0) << 32);
    if (((ready >> idx) & 1) || ++it > SPIN_MAX) break;
  }
}

enum { B_FULL = 0, B_EMPTY = 6, B_S4 = 12, B_S5, B_LAND, B_FLT = B_LAND + 6, B_Z1, B_Z2, B_GO, B_X, B_WM, B_NUM, B_W0 = B_NUM };

__global__ void __launch_bounds__(NTHR, 1)
fused_kernel(const Params p, const __grid_constant__ Maps maps) {
  extern __shared__ __align__(1024) uint8_t smem_raw[];
  const int tid = threadIdx.x, cta = blockIdx.x, t128 = tid & 127;
  const int wp = __shfl_sync(0xffffffffu, tid >> 5, 0), wg = wp >> 2;
  const int l = tid & 31, g = l >> 2, t = l & 3;
  Scratch* const sc = p.s;
  const bool rows = cta < 128;
  const int R = cta - 12;

  uint32_t xr[18];
  uint32_t cv[3];
  const unsigned ep = ld_rlx(&sc->cnt[C_EP]) + 1;
  if (tid == 0) TS(0);
  if (wg == 2) {
#pragma unroll
    for (int i = 0; i < 3; i++) cv[i] = ld_nc(reinterpret_cast<const uint32_t*>(p.c) + min(t128 + 128 * i, 287));
    if (wp == 9 && l < 9 && rows) {
      const int h = 9 * cta + l;
      prefetch_l2(reinterpret_cast<const uint8_t*>(p.wmod) + (size_t)(h >> 1) * (12 * D_) + (h & 1) * (2 * D_), 2 * D_);
    }
    if (tid == 256 && cta < 72) {
      mbar_init(full0 + 8 * B_W0, 1);
      fence_async_smem();
      mbar_expect(full0 + 8 * B_W0, 18432);
#pragma unroll 1
      for (int i = 0; i < 3; i++) tma2d(sbase + O_P2 + i * 6144, &maps.wm, 16 * cta, 192 * i, full0 + 8 * B_W0);
    }
    __syncwarp();
#pragma unroll 1
    for (int u = cta < 72 ? cta : 72 + cta; u < 216; u += u < 72 ? 72 : NCTA) if (u < 72 || t128 < 16) *mod_ptr(sc, u, t128) = 0;
    if (wp == 11 && smem_u32(smem_raw) != sbase) __trap();
    if (wp >= 10 && elect()) {
#pragma unroll 1
      for (int i = wp - 10; i < B_NUM; i += 2) mbar_init(full0 + 8 * i, i == B_FLT ? 4 : i == B_WM ? 3 : i < B_LAND ? 2 : 1);
      fence_async_smem();
    }
    __syncwarp();
  }
  CK(0);
  auto load_x = [&]() {
    const uint32_t* xs = reinterpret_cast<const uint32_t*>(p.x) + (size_t)(cta + 256 * wp) * 288 + l;
#pragma unroll
    for (int i = 0; i < 9; i++) { xr[i] = ld_nc(xs + 32 * i); xr[9 + i] = ld_nc(xs + 128 * 288 + 32 * i); }
  };
  if (rows && wg < 2) load_x();
  if (tid == 64 && cta == NCTA - 1) prefetch_l2(p.tab, sizeof(T_TAB));
  __syncwarp();
  const uint32_t tag16 = (ep & 0x7fffu) | 0x8000u, tag1 = ep & 1u;

  if (wg == 2) {
#pragma unroll
    for (int i = 0; i < 3; i++) {
      const float c0 = bf_lo(cv[i]), c1 = bf_hi(cv[i]);
      sts(red + 512 + min(t128 + 128 * i, 287) * 4, pack_bf16(__fdividef(c0, 1.0f + __expf(-c0)), __fdividef(c1, 1.0f + __expf(-c1))));
    }
    if (wp == 9 && l < 14) asm volatile("prefetch.tensormap [%0];" ::"l"(&maps.z1 + l) : "memory");
    bar_sync(4, 128);
    if (cta < 72) {
      mod_unit(sc, cta, t128, sbase + O_P2, full0 + 8 * B_W0, 0, red, tag16);
      if (t128 == 0) TS(25);
    }
    CK(1);
  }
  const int pi = R / 15, col0 = 20 * (R - 15 * pi);
  const int xu = DF_ * pi + col0, xv = DF_ * (pi ? 16 - pi : 8) + col0;
  auto load_filter = [&](int a) {
    const int x = (a & 1) ? xv : xu;
    const bool wide = (x & 15) > 12;
    mbar_expect(full0 + 8 * B_FLT, wide ? 12288 : 8192);
    tma2d(sbase + O_RAW + a * 12288, &maps.wf[a & 2], x & ~15, 0, full0 + 8 * B_FLT);
    if (wide) tma2d(sbase + O_RAW + a * 12288 + 8192, &maps.wf[(a & 2) + 1], (x & ~15) + 32, 0, full0 + 8 * B_FLT);
  };
  const int kap = 8 * ((wp & 3) ^ (wg & 1)) + g;
  uint4 af[4];
  if (rows) {
    uint32_t tb[4];
#pragma unroll
    for (int i = 0; i < 4; i++) tb[i] = pack_bf16(tmat(cta, 8 * (i >> 1) + g, 2 * t + 8 * (i & 1)), tmat(cta, 8 * (i >> 1) + g, 2 * t + 8 * (i & 1) + 1));
    uint32_t sb1[3], lo[9];
#pragma unroll
    for (int i = 0; i < 4; i++) tb[i] = pin(tb[i]);
#pragma unroll
    for (int i = 0; i < 3; i++) {
      const int d = 48 * wp + 16 * i + (l & 15);
      sb1[i] = pin(sbase + O_B1 + (l >> 4) * 9216 + (d % 9) * 1024 + (d & 63) * 16);
    }
    const uint32_t snt = pin(sbase + O_NRM + ((l & 7) + 8 * (l >> 4)) * 1168 + (48 * wp + (l & 8)) * 2);
    uint2 ms[3], mc[3];
    const uint32_t smask = pin(t ? 0u : 0xffff0000u);
    const uint32_t* const mp = pin(sc->moda + (cta >> 4) * (2 * D_) + 48 * wp + 2 * g);
    auto load_mod = [&]() {
#pragma unroll
      for (int i = 0; i < 3; i++) { ms[i] = ld_rlx2(mp + 16 * i); mc[i] = ld_rlx2(mp + D_ + 16 * i); }
    };
    if (wg < 2) {
#pragma unroll
      for (int k1 = 0; k1 < 9; k1++) lo[k1] = pin(sbase + O_Z1 + line_off(k1, kap, 4 * wg + t, cta & 3));
      float a[18], b[18];
#pragma unroll
      for (int i = 0; i < 9; i++) { a[2 * i] = bf_lo(xr[i]); a[2 * i + 1] = bf_hi(xr[i]); b[2 * i] = bf_lo(xr[9 + i]); b[2 * i + 1] = bf_hi(xr[9 + i]); }
      float oa, ra, ob, rb;
      ln_stats2(a, b, 1.0f, oa, ra, ob, rb);
      CK(1);
      const uint32_t sn = sbase + O_NRM + wp * 2336 + l * 4;
#pragma unroll
      for (int i = 0; i < 9; i++) {
        sts(sn + i * 128, pack_bf16(fmaf(a[2 * i], ra, oa), fmaf(a[2 * i + 1], ra, oa)));
        sts(sn + 1168 + i * 128, pack_bf16(fmaf(b[2 * i], rb, ob), fmaf(b[2 * i + 1], rb, ob)));
      }
      CK(2);
      bar_arrive(10, NTHR);
      load_mod();
#pragma unroll
      for (int kk = 0; kk < 4; kk++) af[kk] = ld_nc4(p.tab + TB_F + kk * 128 + (t128 ^ (wg << 5)));
      bar_sync(1, 256);
      if (tid == 0) TS(2);
    } else {
      bar_sync(10, NTHR);
      load_mod();
      CK(2);
      if (PFF && wp >= 12 - PFF && elect()) prefetch_l2(reinterpret_cast<const uint8_t*>(wp == 10 ? p.wr : p.wi) + cta * 9248, 9248);
      __syncwarp();
    }
    float rs[3][8];
#pragma unroll
    for (int i = 0; i < 3; i++) {
      uint32_t a0, a1, a2, a3;
      asm volatile("ldmatrix.sync.aligned.m8n8.x4.trans.shared.b16 {%0,%1,%2,%3}, [%4];" : "=r"(a0), "=r"(a1), "=r"(a2), "=r"(a3)
                   : "r"(snt + 32 * i) : "memory");
      mma16<false>(&rs[i][0], a0, a1, a2, a3, tb[0], tb[1]);
      mma16<false>(&rs[i][4], a0, a1, a2, a3, tb[2], tb[3]);
    }
    CK(3);
    {
      int it = 0;
#pragma unroll 1
      while (true) {
        uint32_t bad = 0;
#pragma unroll
        for (int i = 0; i < 3; i++) bad |= diff2(ms[i].x, ms[i].y, tag16) | diff2(mc[i].x, mc[i].y, tag16);
        if (!any(bad & 0xffffu) || ++it > SPIN_MAX) break;
        load_mod();
      }
      CK(4);
      if (tid == 0) TS(3);
#pragma unroll
      for (int i = 0; i < 3; i++) {
        const float c0 = bf_hi(mc[i].x), c1 = bf_hi(mc[i].y);
        const float s0 = __uint_as_float(ms[i].x & smask), s1 = __uint_as_float(ms[i].y & smask);
        stmatrix4(sb1[i], pack_bf16(fmaf(rs[i][0], c0, s0), rs[i][1] * c0), pack_bf16(fmaf(rs[i][2], c1, s1), rs[i][3] * c1),
                  pack_bf16(rs[i][4] * c0, rs[i][5] * c0), pack_bf16(rs[i][6] * c1, rs[i][7] * c1));
      }
    }
    fence_async_smem();
    CK(5);
    if (wg == 2) {
      bar_arrive(5, NTHR);
      if (R >= 0 && elect()) load_filter(wp - 8);
      __syncwarp();
    } else {
      bar_sync(5, NTHR);
      CK(6);
      float acc[36];
      const uint32_t db = (((sbase + O_B1 + wg * 9216) & 0x3FFFF) >> 4) | ((128 >> 4) << 16);
      wg_fence();
#pragma unroll
      for (int kk = 0; kk < 4; kk++) wgmma_rs_72(acc, af[kk].x, af[kk].y, af[kk].z, af[kk].w, db + kk * 16, 1024 >> 4, kk);
      wg_commit();
      wg_wait<0>();
      reg_fence(acc);
      CK(7);
      float2 za[9], zb[9];
#pragma unroll
      for (int i = 0; i < 9; i++) { za[i] = make_float2(acc[4 * i], acc[4 * i + 2]); zb[i] = make_float2(acc[4 * i + 1], acc[4 * i + 3]); }
      dft9(za); dft9(zb);
      if (kap == 0) {
#pragma unroll
        for (int k = 1; k < 5; k++) {
          float2 a = za[k], b = za[9 - k];
          za[k] = make_float2(a.x + b.x, a.y - b.y); za[9 - k] = make_float2(a.y + b.y, b.x - a.x);
          a = zb[k]; b = zb[9 - k];
          zb[k] = make_float2(a.x + b.x, a.y - b.y); zb[9 - k] = make_float2(a.y + b.y, b.x - a.x);
        }
        sts2(lo[0] + 288 * 8, set_tag(pack_bf16(za[0].y, 0.f), tag1), pack_bf16(zb[0].y, 0.f));
        za[0].y = 0.f; zb[0].y = 0.f;
      }
      __syncwarp();
#pragma unroll
      for (int k1 = 0; k1 < 9; k1++) sts2(lo[k1], set_tag(pack_bf16(za[k1].x, za[k1].y), tag1), pack_bf16(zb[k1].x, zb[k1].y));
      fence_async_smem();
      CK(8);
      bar_arrive(2 + wg, 160);
      {
        const uint32_t fx = (((cta >> 4) ^ cta) & 3) << 3, dl = O_IN - O_Z1, st = sbase + O_ST + 15360 + tid * 16;
        sts4(st, (lo[0] ^ fx) + dl, (lo[1] ^ fx) + dl, (lo[2] ^ fx) + dl, (lo[3] ^ fx) + dl);
        sts4(st + 4096, (lo[4] ^ fx) + dl, (lo[5] ^ fx) + dl, (lo[6] ^ fx) + dl, (lo[7] ^ fx) + dl);
        sts4(st + 8192, (lo[8] ^ fx) + dl, (lo[0] ^ fx) + dl + (kap ? 0 : 288 * 8),
             sbase + O_B3 + wg * 1024 + (l >> 4) * 2048 + (2 * (kap & 24) + (l & 15)) * 16, 0);
      }
    }
    {
      uint32_t sy[6];
#pragma unroll
      for (int i = 0; i < 6; i++) {
        const int rr = 16 * (wp & 3) + g + 8 * (i & 1);
        sy[i] = sbase + O_Y + (t * 584 + 64 * ((3 * wg + (i >> 1) + 63 - rr) % 9) + rr) * 4;
      }
      sts4(sbase + O_ST + tid * 16, movm(tb[0]), movm(tb[2]), movm(tb[1]), movm(tb[3]));
      sts4(sbase + O_ST + 6144 + tid * 16, sy[0], sy[1], sy[2], sy[3]);
      sts2(sbase + O_ST + 12288 + tid * 8, sy[4], sy[5]);
    }
  } else {
    __syncthreads();
  }

  if ((wp >> 1) == 4) {
    if (rows) {
      const int slot = 4 * (cta & 7) + ((cta >> 4) & 3) + 32 * (2 * (cta >> 6) + ((cta >> 3) & 1));
      const uint32_t c0 = upin(40 * slot), c1 = upin(60 * (wp - 8)), src = upin(sbase + O_Z1 + (wp - 8) * 9600);
      const CUtensorMap* mp = upin(&maps.z1);
      unsigned* hint = pin(&sc->cnt[C_Z1 + 32 * (wp - 8)]);
      bar_sync(wp - 6, 160);
      if (elect()) {
        tma_st2d(mp, src, c0, c1);
        HW();
        red_add(hint, 1);
        if (wp == 8) TS(4);
      }
    } else {
      int it = 0;
      while (any((ld_rlx(sc->moda + 36 * l) ^ tag16) & 0xffffu) && ++it < SPIN_MAX) {}
      if (elect()) { load_filter(wp - 8); load_filter(wp - 6); }
    }
    __syncwarp();
  }
  auto load_wm = [&](int u) {
    if (wp > 8 && elect()) {
      mbar_expect(full0 + 8 * B_WM, 6144);
      tma2d(sbase + O_NRM + (wp - 9) * 6144, &maps.wm, 16 * u, 192 * (wp - 9), full0 + 8 * B_WM);
    }
    __syncwarp();
  };
  if (R >= 0) {
    const int nl = (col0 + wp < DF_) + (wg < 2 && col0 + wp + 12 < DF_);
    uint4 cf[2][4], G[4];
#pragma unroll
    for (int i = 0; i < 4; i++) {
      cf[0][i] = __ldg(p.tab + TB_P2 + i * 32 + l);
      cf[1][i] = __ldg(p.tab + TB_P2 + (pi ? i : 4 + i) * 32 + l);
      G[i] = __ldg(p.tab + TB_P2 + (8 + i) * 32 + l);
    }
    const uint32_t* zin = sc->z1 + (size_t)R * 5120;
    if (wp == 10) {
      const uint32_t* zu = upin(zin);
      if (elect()) mbar_expect(full0 + 8 * B_Z1, 20480);
      wait_cnt(&sc->cnt[C_Z1 + 32 * (pi >> 2)], 128 * ep);
      if (elect()) {
        bulk_ld(sbase + O_P2, zu, 20480, full0 + 8 * B_Z1);
        TS(12);
      }
      __syncwarp();
    }
    mbar_wait(full0 + 8 * B_FLT, 0);
    CK(9);
    float wn[16], wc[16];
#pragma unroll 1
    for (int ln = nl - 1; ln >= 0; ln--) {
      const int col = col0 + wp + 12 * ln, k2 = (57 * col) & 63;
      const bool cj = k2 > 32 || (k2 == 32 && col != 288);
      const float nr = ((col & 31) == 0 && col != 0 && col != 288 ? 0.5f : 1.0f) / ((float)S_ * D_), ni = cj ? -nr : nr;
#pragma unroll
      for (int i = 0; i < 16; i++) wn[i] = wc[i];
#pragma unroll
      for (int cl = 0; cl < 2; cl++) {
        const int v = cl ^ (cj && pi), e = ((v ? xv : xu) & 15) + wp + 12 * ln, sh = e < 32 ? 6 : 5;
        const uint32_t base = sbase + O_RAW + v * 12288 + (e < 32 ? 2 * e : 8192 - 64 + 2 * e), msk = e < 32 ? 0x30 : 0x10;
        const int dm = v ? (cj || pi ? -1 : 0) : 0;
#pragma unroll
        for (int tt = 0; tt < 4; tt++) {
          const int kc = g + 64 * (tt >> 1) + 16 * t + 8 * (tt & 1);
          uint32_t a = base + ((((cj ? -kc : kc) + dm) & 127) << sh);
          a ^= (a >> 3) & msk;
          wc[4 * tt + 2 * cl] = lds_bf(a) * nr; wc[4 * tt + 2 * cl + 1] = lds_bf(a + 24576) * ni;
        }
      }
    }
    const float al = __uint_as_float(pin((pi ? 0x3f800000u : 0u) + (l >> 5)));
    const uint32_t tagv = pin(tag1 + (l >> 5));
    CK(10);
    uint32_t off = pin(l * 160 + ((wp ^ (g & 3)) << 3));
    uint32_t offo = pin(sbase + O_P2 + 20480 + off - 64 * l), po = 3072;
    unsigned* hz2 = pin(&sc->cnt[C_Z2]);
    const uint32_t do2 = pin(12288 - 32 * l);
    const CUtensorMap* mz2 = upin(&maps.z2[wp == 0]);
    const uint32_t sz2 = upin(sbase + O_P2 + 20480 + (wp ? 0 : 12288)), cz2 = upin(40 * R + (wp ? 0 : 24));
    mbar_wait(full0 + 8 * B_Z1, 0);
    CK(11);
    if (tid == 0) TS(8);
    if (wg == 2) load_wm(72 + cta);
    uint2 v[4], v2[4];
    const uint32_t o2 = nl > 1 ? 96 : 0;
#pragma unroll
    for (int i = 0; i < 4; i++) { v[i] = lds2(sbase + O_P2 + off + i * 5120); v2[i] = lds2(sbase + O_P2 + off + o2 + i * 5120); }
    auto bad2 = [&]() {
      return any(or3(or3(diff2(v[0].x, v[1].x, tagv), diff2(v[2].x, v[3].x, tagv), diff2(v2[0].x, v2[1].x, tagv)), diff2(v2[2].x, v2[3].x, tagv), 0) & 1);
    };
    if (__builtin_expect(bad2() && nl, 0)) {
      FAILCNT(0);
      int it = 0;
      do {
#pragma unroll
        for (int i = 0; i < 4; i++) {
          v[i] = ld_rlx2(reinterpret_cast<const uint8_t*>(zin) + off + i * 5120);
          v2[i] = ld_rlx2(reinterpret_cast<const uint8_t*>(zin) + off + o2 + i * 5120);
        }
      } while (bad2() && ++it < SPIN_MAX);
    }
#pragma unroll 1
    for (int ln = 0; ln < nl; ln++, offo += do2, po = 2048) {
      float d[4][4];
      uint32_t A[8];
#pragma unroll
      for (int h = 0; h < 2; h++) {
        mma16<false>(d[2 * h], cf[0][0].x, cf[0][0].y, cf[0][0].z, cf[0][0].w, v[h].x, v[2 + h].x);
        mma16<false>(d[2 * h + 1], cf[1][0].x, cf[1][0].y, cf[1][0].z, cf[1][0].w, v[h].y, v[2 + h].y);
      }
      if (ln) { fence_async_smem(); bar_arrive(15, NTHR); }
#pragma unroll
      for (int h = 0; h < 2; h++)
#pragma unroll
        for (int L = 0; L < 2; L++) {
          const uint4 tw = cf[L][2 + h];
          const float* z = d[2 * h + L];
          const float2 z0 = cmul(make_float2(z[0], z[2]), make_float2(__uint_as_float(tw.x), __uint_as_float(tw.y)));
          const float2 z1 = cmul(make_float2(z[1], z[3]), make_float2(__uint_as_float(tw.z), __uint_as_float(tw.w)));
          A[4 * h + L] = pack_bf16(z0.x, z0.y); A[4 * h + 2 + L] = pack_bf16(z1.x, z1.y);
        }
#pragma unroll
      for (int tt = 0; tt < 4; tt++) {
        mma16<false>(d[tt], A[0], A[1], A[2], A[3], G[tt].x, G[tt].y);
        mma16<true>(d[tt], A[4], A[5], A[6], A[7], G[tt].z, G[tt].w);
      }
#pragma unroll
      for (int tt = 0; tt < 4; tt++) {
        const float ar = d[tt][0], aj = d[tt][1], br = d[tt][2], bj = d[tt][3];
        const float2 y1 = cmul(make_float2(fmaf(-al, bj, ar), fmaf(al, br, aj)), make_float2(wc[4 * tt], wc[4 * tt + 1]));
        const float2 y2 = cmul(make_float2(fmaf(al, ar, bj), fmaf(al, aj, -br)), make_float2(wc[4 * tt + 2], wc[4 * tt + 3]));
        A[2 * tt] = pack_bf16(fmaf(al, y2.x, y1.x), fmaf(-al, y2.y, -y1.y));
        A[2 * tt + 1] = pack_bf16(fmaf(al, y1.y, -y2.y), fmaf(al, y1.x, -y2.x));
      }
#pragma unroll
      for (int i = 0; i < 16; i++) wc[i] = wn[i];
#pragma unroll
      for (int i = 0; i < 4; i++) v[i] = v2[i];
#pragma unroll
      for (int tt = 0; tt < 4; tt++) {
        mma16<false>(d[tt], A[0], A[1], A[2], A[3], G[tt].x, G[tt].y);
        mma16<true>(d[tt], A[4], A[5], A[6], A[7], G[tt].z, G[tt].w);
      }
#pragma unroll
      for (int h = 0; h < 2; h++)
#pragma unroll
        for (int L = 0; L < 2; L++) {
          const uint4 tw = cf[L][2 + h];
          const float2 z0 = cmul(make_float2(d[2 * h][2 * L], d[2 * h][2 * L + 1]), make_float2(__uint_as_float(tw.x), __uint_as_float(tw.y)));
          const float2 z1 = cmul(make_float2(d[2 * h + 1][2 * L], d[2 * h + 1][2 * L + 1]), make_float2(__uint_as_float(tw.z), __uint_as_float(tw.w)));
          A[4 * h + 2 * L] = movm(pack_bf16(z0.x, z1.x)); A[4 * h + 2 * L + 1] = movm(pack_bf16(z0.y, z1.y));
        }
#pragma unroll
      for (int h = 0; h < 2; h++) {
        mma16<false>(d[0], cf[0][1].x, cf[0][1].y, cf[0][1].z, cf[0][1].w, A[4 * h], A[4 * h + 1]);
        mma16<false>(d[1], cf[1][1].x, cf[1][1].y, cf[1][1].z, cf[1][1].w, A[4 * h + 2], A[4 * h + 3]);
#pragma unroll
        for (int e = 0; e < 2; e++)
          sts2(offo + (2 * h + e) * po, set_tag(pack_bf16(d[0][e], d[0][2 + e]), tagv), pack_bf16(d[1][e], d[1][2 + e]));
      }
      CK(12 + ln);
    }
    fence_async_smem();
    if (nl < 2 && wp != 8) bar_arrive(15, NTHR);
    if (wp & 7) { if (wg < 2) bar_arrive(6, 256); }
    else {
      if (wp) bar_sync(15, NTHR); else bar_sync(6, 256);
      if (elect()) {
        tma_st2d(mz2, sz2, cz2, 0);
        HW();
        if (wp == 0) { red_add(hz2, 1); TS(9); }
      }
      __syncwarp();
    }
  }
  if (wg == 2) {
#pragma unroll 1
    for (int u = 72 + cta, k = 0; u < 216; u += NCTA, k ^= 1) {
      if (R < 0) { fence_async_smem(); bar_sync(4, 128); load_wm(u); }
      mod_unit(sc, u, t128, sbase + O_NRM, full0 + 8 * B_WM, k, red + 256 - 256 * k, tag16);
    }
    fence_async_smem();
    CK(13);
  }

  const int grp = cta / 11, m1 = cta - 11 * grp;
  const bool helper = (m1 & 3) == 3;
  const int f1 = 384 * grp + (helper ? 192 : 128) * (m1 >> 2);
  const int d1 = 160 * (m1 & 3), flip = m1 >= 7;
  const int a1bytes = helper ? 24576 : 16384;
  auto load_a1 = [&](int st, int kb) {
    mbar_expect(full0 + 8 * st, a1bytes);
    tma4d_ef(sbase + st * STAGE, helper ? &maps.w1b : &maps.w1a, 4 * (kb >> 3), 16 * (kb & 7), f1 >> 6, full0 + 8 * st);
  };

  if (rows) {
#pragma unroll
    for (int kk = 0; kk < 4; kk++) af[kk] = __ldg(p.tab + TB_E + kk * 128 + t128);
    const uint4 c0 = lds4(sbase + O_ST + tid * 16), c1 = lds4(sbase + O_ST + 6144 + tid * 16);
    const uint2 c2 = lds2(sbase + O_ST + 12288 + tid * 8);
    const uint32_t tb[4] = {c0.x, c0.y, c0.z, c0.w}, sy[6] = {c1.x, c1.y, c1.z, c1.w, c2.x, c2.y};
    const uint32_t l8 = pin(8 * l), syl = pin(sbase + O_Y + wp * 2336 + 8 * l);
    const uint32_t sh3 = pin(sbase + O_B3 + (wp >> 1) * 4608 + (l >> 4) * 256 + (wp & 1) * 128 + ((((l >> 2) ^ (2 * cta + (wp & 1))) & 3) << 4) + (l & 3) * 4);
    const bool htag = (((sh3 >> 2) ^ (2 * cta + (wp & 1))) & 7) == 0;
    const uint32_t ham = pin(htag ? ~1u : ~0u), hom = pin(htag ? tag1 : 0u);
    const int slot = 4 * (cta >> 4) + ((cta >> 1) & 3) + 32 * (2 * ((cta >> 3) & 1) + (cta & 1));
    const uint32_t* zin = sc->z2 + (size_t)slot * 4800;
    if (wg == 2) {
      {
        uint4 v[4];
        const int i3 = min(t128 + 384, 431);
        int it = 0;
        while (true) {
          uint32_t bad = 0;
#pragma unroll
          for (int k = 0; k < 4; k++) v[k] = ld_rlx4(sc->mod + 4 * (k < 3 ? t128 + 128 * k : i3));
#pragma unroll
          for (int k = 0; k < 4; k++) {
            v[k].x ^= tag16; v[k].y ^= tag16; v[k].z ^= tag16; v[k].w ^= tag16;
            bad |= v[k].x | v[k].y | v[k].z | v[k].w;
          }
          if (!any(bad & 0xffffu) || ++it > SPIN_MAX) break;
        }
#pragma unroll
        for (int k = 0; k < 4; k++) sts4(sbase + O_MOD + 16 * (k < 3 ? t128 + 128 * k : i3), v[k].x, v[k].y, v[k].z, v[k].w);
      }
      CK(14);
      bar_sync(10, NTHR);
      mbar_wait(full0 + 8 * B_Z2, 0);
      if (elect()) {
        load_a1(wp - 8, wp - 8);
        if (wp > 8 && wp - 8 < NG1) prefetch_l2(reinterpret_cast<const uint8_t*>(p.w1) + (size_t)(128 * (4 * ((wp - 8) >> 1) + (cta >> 5)) + 64 * (wp & 1) + 2 * (cta & 31)) * (2 * F_), 4 * F_);
      }
      __syncwarp();
    } else {
      const uint4 e0 = lds4(sbase + O_ST + 15360 + tid * 16), e1 = lds4(sbase + O_ST + 19456 + tid * 16), e2 = lds4(sbase + O_ST + 23552 + tid * 16);
      const uint32_t lo[9] = {e0.x, e0.y, e0.z, e0.w, e1.x, e1.y, e1.z, e1.w, e2.x}, lx = e2.y, sb3 = e2.z;
      bar_arrive(10, NTHR);
      CK(14);
      if (wp == 1) {
        const uint32_t* zu = upin(zin);
        if (elect()) mbar_expect(full0 + 8 * B_Z2, 19200);
        wait_cnt(&sc->cnt[C_Z2], 120 * ep);
        if (elect()) {
          bulk_ld(sbase + O_IN, zu, 19200, full0 + 8 * B_Z2);
          TS(14);
        }
        __syncwarp();
      }
      mbar_wait(full0 + 8 * B_Z2, 0);
      CK(15);
      if (tid == 0) TS(11);
      uint2 v[10];
#pragma unroll
      for (int k1 = 0; k1 < 10; k1++) v[k1] = lds2(k1 < 9 ? lo[k1] : lx);
      auto bad3 = [&]() {
        return any(or3(or3(diff2(v[0].x, v[1].x, tag1), diff2(v[2].x, v[3].x, tag1), diff2(v[4].x, v[5].x, tag1)), diff2(v[6].x, v[7].x, tag1), diff2(v[8].x, v[9].x, tag1)) & 1);
      };
      if (__builtin_expect(bad3(), 0)) {
        FAILCNT(1);
        int it = 0;
        do {
#pragma unroll
          for (int k1 = 0; k1 < 10; k1++) v[k1] = ld_rlx2(reinterpret_cast<const uint8_t*>(zin) + ((k1 < 9 ? lo[k1] : lx) - (sbase + O_IN)));
        } while (bad3() && ++it < SPIN_MAX);
      }
      float2 za[9], zb[9];
#pragma unroll
      for (int i = 0; i < 9; i++) { za[i] = make_float2(bf_lo(v[i].x), bf_hi(v[i].x)); zb[i] = make_float2(bf_lo(v[i].y), bf_hi(v[i].y)); }
      if (kap == 0) {
#pragma unroll
        for (int k = 1; k < 5; k++) {
          float2 a = za[k], b = za[9 - k];
          za[k] = make_float2(a.x - b.y, a.y + b.x); za[9 - k] = make_float2(a.x + b.y, b.x - a.y);
          a = zb[k]; b = zb[9 - k];
          zb[k] = make_float2(a.x - b.y, a.y + b.x); zb[9 - k] = make_float2(a.x + b.y, b.x - a.y);
        }
        za[0].y = bf_lo(v[9].x); zb[0].y = bf_lo(v[9].y);
      }
      __syncwarp();
      dft9(za); dft9(zb);
#pragma unroll
      for (int n = 0; n < 8; n += 2) {
        const int i0 = (9 - n) % 9, i1 = 8 - n;
        stmatrix4(sb3 + n * 2048, pack_bf16(za[i0].x, zb[i0].x), pack_bf16(za[i0].y, zb[i0].y), pack_bf16(za[i1].x, zb[i1].x), pack_bf16(za[i1].y, zb[i1].y));
      }
      stmatrix2(sb3 + 8 * 2048, pack_bf16(za[1].x, zb[1].x), pack_bf16(za[1].y, zb[1].y));
      fence_async_smem();
    }
    CK(16);
    __syncthreads();
    CK(17);
    float acc[24];
    const uint32_t db = (((sbase + O_B3 + wg * 6144) & 0x3FFFF) >> 4) | ((128 >> 4) << 16);
    wg_fence();
#pragma unroll
    for (int kk = 0; kk < 4; kk++) wgmma_rs_48(acc, af[kk].x, af[kk].y, af[kk].z, af[kk].w, db + kk * 16, 1024 >> 4, kk);
    wg_commit();
    uint32_t ga[9];
    uint2 sh[9], sw[9];
    if (wg < 2) {
#pragma unroll
      for (int i = 0; i < 9; i++) {
        const uint2 v = lds2(l8 + sbase + O_MOD + 256 * i);
        ga[i] = __byte_perm(v.x, v.y, 0x7632);
        sh[i] = lds2(l8 + sbase + O_MOD + 4 * D_ + 256 * i);
        sw[i] = lds2(l8 + sbase + O_MOD + 8 * D_ + 256 * i);
      }
    }
    wg_wait<0>();
    reg_fence(acc);
    CK(18);
#pragma unroll
    for (int i = 0; i < 3; i++) {
      const float* a = &acc[8 * i];
      const uint32_t a0 = pack_bf16(a[0], a[1]), a1 = pack_bf16(a[2], a[3]), a2 = pack_bf16(a[4], a[5]), a3 = pack_bf16(a[6], a[7]);
#pragma unroll
      for (int jh = 0; jh < 2; jh++) {
        float y[4];
        mma16<false>(y, a0, a1, a2, a3, tb[2 * jh], tb[2 * jh + 1]);
        sts(sy[2 * i] + jh * (4 * 584 * 4), pack_bf16(y[0], y[1]));
        sts(sy[2 * i + 1] + jh * (4 * 584 * 4), pack_bf16(y[2], y[3]));
      }
    }
    CK(19);
    if (wg == 2) bar_arrive(7, NTHR);
    else {
      bar_sync(7, NTHR);
      CK(20);
      float a[18], b[18];
#pragma unroll
      for (int i = 0; i < 9; i++) {
        const uint2 y = lds2(syl + 256 * i);
        xr[i] = hfma2(ga[i], __byte_perm(y.x, y.y, 0x5410), xr[i]);
        xr[9 + i] = hfma2(ga[i], __byte_perm(y.x, y.y, 0x7632), xr[9 + i]);
        a[2 * i] = bf_lo(xr[i]); a[2 * i + 1] = bf_hi(xr[i]); b[2 * i] = bf_lo(xr[9 + i]); b[2 * i + 1] = bf_hi(xr[9 + i]);
      }
      float oa, ra, ob, rb;
      ln_stats2(a, b, 1.0f, oa, ra, ob, rb);
      CK(21);
#pragma unroll
      for (int i = 0; i < 9; i++) {
        const float c0 = __uint_as_float(sw[i].x), c1 = __uint_as_float(sw[i].y), s0 = __uint_as_float(sh[i].x), s1 = __uint_as_float(sh[i].y);
        a[2 * i] = fmaf(fmaf(a[2 * i], ra, oa), c0, s0); a[2 * i + 1] = fmaf(fmaf(a[2 * i + 1], ra, oa), c1, s1);
        b[2 * i] = fmaf(fmaf(b[2 * i], rb, ob), c0, s0); b[2 * i + 1] = fmaf(fmaf(b[2 * i + 1], rb, ob), c1, s1);
      }
      ln_stats2(a, b, 0.5f, oa, ra, ob, rb);
      CK(22);
#pragma unroll
      for (int i = 0; i < 9; i++) {
        sts(sh3 + i * 512, and_or(pack_bf16(fmaf(a[2 * i], ra, oa), fmaf(a[2 * i + 1], ra, oa)), ham, hom));
        sts(sh3 + i * 512 + 64, and_or(pack_bf16(fmaf(b[2 * i], rb, ob), fmaf(b[2 * i + 1], rb, ob)), ham, hom));
      }
      fence_async_smem();
      if (wp < 2 * H3G) bar_arrive(8, 32 + 64 * H3G); else bar_arrive(9, 288 - 64 * H3G);
      CK(23);
    }
  } else __syncthreads();

  const bool g2 = cta < 130 && (cta >> 1) != 56;
  const int z2 = cta < 112 ? cta : cta - 2, r = z2 >> 6;
  const int s2 = 128 * ((z2 >> 2) & 15), d2 = 144 * (z2 & 3);
  constexpr int XST = (33 + 36 - JSK - 1) % NST;
  constexpr int ST0 = (32 - JSK - 1) % NST, ST1 = 31 % NST;

  if (wg == 2) {
    asm volatile("setmaxnreg.dec.sync.aligned.u32 40;");
    auto load_b = [&](bool second, int i, int st) {
      const uint32_t lb = full0 + 8 * (B_LAND + st), bytes = second ? 18432 : STAGE - a1bytes;
      mbar_expect(lb, bytes);
      bulk_ld(sbase + (second ? st * STAGE2 + 16384 : st * STAGE + a1bytes),
              second ? sc->u + ((size_t)(36 * r + kb2_order(i)) * D_ + d2) * 128 : sc->h3 + ((size_t)(i * 18 + (d1 >> 5)) << 12), bytes, lb);
    };
    if (wp == 8) {
      int st = rows ? 4 : 0, ph = 1;
#pragma unroll 1
      for (int kb = st; kb < 32; kb++) {
        if (rows && (kb >> 1) == 2) mbar_wait(full0 + 8 * (B_S4 - 4 + kb), 0);
        mbar_wait(empty0 + 8 * st, ph);
        if (elect()) {
          load_a1(st, kb);
          if (kb >= PF2K && kb < PF2K + PF2 && g2)
            prefetch_l2(reinterpret_cast<const uint8_t*>(p.w2) + (size_t)(36 * r + kb2_order(kb - PF2K)) * 262144 + (z2 & 63) * 4096, 4096);
        }
        __syncwarp();
        ring_next<false>(st, ph);
      }
      if (g2) {
        st++;
#pragma unroll 1
        for (int i = 0; i < 36; i++) {
          if (i == HOLDA) mbar_wait(full0 + 8 * B_GO, 0);
          mbar_wait(empty0 + 8 * st, ph);
          if (elect()) {
            mbar_expect(full0 + 8 * st, 16384);
            tma3d_ef(sbase + st * STAGE2, &maps.w2, 64 * (36 * r + kb2_order(i)), s2 >> 6, full0 + 8 * st);
          }
          __syncwarp();
          ring_next<true>(st, ph);
        }
      }
    } else if (wp >= 10) {
      const int sw = wp - 10;
      if (rows) {
        const CUtensorMap* mp = upin(&maps.h3[sw]);
        const uint32_t src = upin(sbase + O_B3 + sw * (H3G * 4608)), c0 = upin(64 * (cta & 15)), c1 = upin(18 * (cta >> 4)), c2 = upin(H3G * sw);
        unsigned* flag = pin(&sc->cnt[C_H3 + (cta >> 4) + 8 * sw]);
        bar_sync(8 + sw, sw ? 288 - 64 * H3G : 32 + 64 * H3G);
        if (sw) mbar_wait(full0 + 8 * H3W, 0);
        if (elect()) {
          tma_st3d(mp, src, c0, c1, c2);
          mbar_arrive(full0 + 8 * B_S4);
          bulk_commit_wait();
          red_add(flag, 1);
          mbar_arrive(full0 + 8 * B_S5);
          TS(sw ? 24 : 13);
        }
        __syncwarp();
      }
      if (sw) {
        if (rows) {
          mbar_wait(full0 + 8 * B_S5, 0);
          if (elect()) { asm volatile("fence.acq_rel.gpu;" ::: "memory"); red_add(&sc->cnt[C_X + 64], 1); }
          __syncwarp();
        }
        wait_cnt(&sc->cnt[C_X + 64], 128 * ep);
        if (elect()) mbar_arrive(full0 + 8 * B_X);
        __syncwarp();
      }
      if (sw && g2) {
#pragma unroll 1
        for (int i = 0; i < 36; i++) { sc->part[z2 * 1152 + 32 * i + l] = make_uint4(tag1 ^ 1, 0, 0, 0); __nanosleep(100); }
        __syncwarp();
      }
      uint32_t lph = 0;
      auto check_tiles = [&](bool second, int n, int st, uint32_t o1, uint32_t d2nd) {
        const uint32_t b1 = pin(sbase + o1), b2 = pin(sbase + o1 + d2nd);
        int i = 0, it = 0;
#pragma unroll 1
        do {
          const uint32_t so = st * (second ? STAGE2 : STAGE);
          mbar_wait(full0 + 8 * (B_LAND + st), (lph >> st) & 1);
          lph ^= 1u << st;
          uint32_t v[20];
#pragma unroll
          for (int k = 0; k < 20; k++) if (!second || k < 10 || k >= 12) v[k] = lds(k < 12 ? b1 + so + k * 1024 : b2 + so + (k - 12) * 1024); else v[k] = tag1;
#pragma unroll
          for (int k = 0; k < 10; k++) v[k] = diff2(v[2 * k], v[2 * k + 1], tag1);
          const uint32_t bad = or3(or3(or3(v[0], v[1], v[2]), or3(v[3], v[4], v[5]), v[6]), v[7], or3(v[8], v[9], 0));
          if (__builtin_expect(any(bad & 1) && ++it < SPIN_MAX, 0)) {
            FAILCNT(2 + second);
            fence_async_smem();
            __syncwarp();
            if (elect()) load_b(second, i, st);
            __syncwarp();
            continue;
          }
          if (elect()) mbar_arrive(full0 + 8 * st);
          if (++st == NST) st = 0;
          i++;
        } while (i < n);
      };
      if (!sw) check_tiles(false, NV1, 0, a1bytes + l * 32 + (l >> 2) * 4, helper ? 4096 : 12288);
      const bool first = helper || m1 < W0N;
#pragma unroll 1
      for (int k = sw ? first : !first; k <= sw; k++) {
        const uint32_t stg = sbase + (!k ? ST0 * STAGE : helper ? ST1 * STAGE : O_U1);
        const int kbA = (f1 >> 6) + (helper ? 2 : 1) * (k ^ flip), kbB = helper ? (f1 >> 6) + 1 : kbA;
        uint8_t* const uA = upin(sc->u + ((size_t)kbA * D_ + d1) * 128);
        uint8_t* const uB = upin(sc->u + ((size_t)kbB * D_ + (helper ? d1 : d1 + 96)) * 128);
        unsigned* const fA = pin(&sc->cnt[C_U + kbA]);
        unsigned* const fB = pin(&sc->cnt[C_U + kbB]);
        const bool slow = sw && !helper;
        bar_sync(11 + k, 160);
        if (!slow) { if (elect()) { bulk_st(uA, stg, 96 * 128); TS(k ? 31 : 30); } __syncwarp(); }
        bar_sync(13 + k, 160);
        if (slow) {
          if (g2) mbar_wait(full0 + 8 * B_GO, 0);
          if (first) pause(10 * TRK0);
#pragma unroll 1
          for (int i = 0; i < 20480; i += 2048) {
            if (elect()) bulk_st(uA + i, stg + i, 2048);
            pause(k ? TRKC : TRK0);
          }
        }
        if (elect()) {
          if (helper ? k : !slow) bulk_st(uB, stg + 96 * 128, helper ? 96 * 128 : 64 * 128);
          bulk_commit_wait();
          red_add(fA, 1);
          if (helper && k) red_add(fB, 1);
          if (!k || helper) mbar_arrive(empty0 + 8 * (k ? ST1 : ST0));
          TS(k ? 23 : 17);
          mbar_arrive(full0 + 8 * B_S5);
        }
        __syncwarp();
      }
      if (sw) {
        mbar_wait(full0 + 8 * B_S5, rows);
        if (elect()) { asm volatile("fence.acq_rel.gpu;" ::: "memory"); red_add(&sc->cnt[C_X], 1); }
        __syncwarp();
      }
      if (g2) {
        if (!sw) check_tiles(true, NV2, 3, 16384 + l * 32 + (4 * (g & 1) + (g >> 1)) * 4, 10240);
        else {
          wait_cnt(&sc->cnt[C_X], NCTA * ep);
          if (elect()) mbar_arrive(full0 + 8 * B_X);
        }
      }
      __syncwarp();
    } else {
      uint64_t ready = 0;
      int st = 0, ph = 1;
#pragma unroll 1
      for (int kb = 0; kb < 32; kb++) {
        const uint8_t* src = upin(sc->h3 + ((size_t)(kb * 18 + (d1 >> 5)) << 12));
        const uint32_t dst = upin(sbase + st * STAGE + a1bytes), lb = full0 + 8 * ((kb < NV1 ? B_LAND : 0) + st);
        if (kb == NV1) { mbar_wait(full0 + 8 * B_X, 0); fence_async_glb(); ready = ~0ull; }
        if (rows && (kb >> 1) == 2) mbar_wait(full0 + 8 * (B_S4 - 4 + kb), 0);
        mbar_wait(empty0 + 8 * st, ph);
        if (elect()) mbar_expect(lb, STAGE - a1bytes);
        wait_flags(sc->cnt + C_H3, 32, (kb & 7) + (kb < 8 * H3G ? 0 : 8), 16 * ep, ready);
        if (elect()) bulk_ld(dst, src, STAGE - a1bytes, lb);
        ring_next<false>(st, ph);
      }
      if (g2) {
        ready = 0;
        st++;
#pragma unroll 1
        for (int i = 0; i < 36; i++) {
          const int kb = kb2_order(i);
          const uint8_t* src = upin(sc->u + ((size_t)(36 * r + kb) * D_ + d2) * 128);
          const uint32_t dst = upin(sbase + st * STAGE2 + 16384), lb = full0 + 8 * ((i < NV2 ? B_LAND : 0) + st);
          if (i == NV2) { mbar_wait(full0 + 8 * B_X, 1); fence_async_glb(); ready = ~0ull; }
          mbar_wait(empty0 + 8 * st, ph);
          if (elect()) mbar_expect(lb, 18432);
          wait_flags(sc->cnt + C_U + 36 * r, 36, kb, 4 * ep, ready);
          if (elect()) {
            bulk_ld(dst, src, 18432, lb);
            if (i == GOAT) mbar_arrive(full0 + 8 * B_GO);
          }
          ring_next<true>(st, ph);
        }
        mbar_wait(empty0 + 8 * st, ph);
        if (elect()) {
          mbar_arrive(full0 + 8 * XST);
          mbar_expect(full0 + 8 * XST, 18432);
#pragma unroll 1
          for (int i = 0; i < 3; i++) tma2d(sbase + XST * STAGE2 + i * 6144, &maps.x1, d2 + 48 * i, s2 + 64 * (r ^ 1), full0 + 8 * XST);
        }
        __syncwarp();
      }
    }
  } else {
    asm volatile("setmaxnreg.inc.sync.aligned.u32 232;");
    const int wgu = wg;
    constexpr uint32_t sb4 = sbase >> 4;
    const int w = wp & 3;
    Ring rg = {0, 0};
    uint32_t* const x1p = sc->x1 + (size_t)(cta + 256 * wp) * 288 + l;
    const uint32_t ad = pin(sbase + (!wg ? ST0 * STAGE : helper ? ST1 * STAGE : O_U1) + (8 * (l >> 4) + (l & 7)) * 128 + (((2 * w + ((l >> 3) & 1)) ^ (l & 7)) << 4));
    const uint32_t uam = pin(g == 2 * t ? 0xfffefffeu : ~0u), uom = pin(g == 2 * t ? tag1 * 0x10001u : 0u);
    float acc[96];
    constexpr uint32_t LA = (8192 >> 4) << 16, LB = (4096 >> 4) << 16;
    {
      const int fa = f1 + (helper ? 128 : 64) * (wg ^ flip) + 16 * w + g, fb = helper ? f1 + 64 + 16 * w + g : fa;
      const float a0 = 0.5f * __bfloat162float(p.b1[fa]), a1 = 0.5f * __bfloat162float(p.b1[fa + 8]);
      const float b0 = 0.5f * __bfloat162float(p.b1[fb]), b1 = 0.5f * __bfloat162float(p.b1[fb + 8]);
#pragma unroll
      for (int i = 0; i < 96; i++) acc[i] = i < 48 ? ((i & 2) ? a1 : a0) : ((i & 2) ? b1 : b0);
      reg_fence(acc);
    }
    if (!helper) gemm_main<0>(acc, sb4 + (wgu ^ flip) * 512 + LA, 0, sb4 + 1024 + LB, wgu, rg, x1p, xr);
    else {
      float ac2[96];
#pragma unroll
      for (int i = 0; i < 96; i++) asm volatile("mov.b32 %0, %1;" : "=f"(ac2[i]) : "f"(acc[i]));
      gemm_main<1>(ac2, sb4 + (wgu ^ flip) * 1024 + LA, sb4 + 512 + LA, sb4 + 1536 + LB, wgu, rg, x1p, xr);
#pragma unroll
      for (int i = 0; i < 96; i++) asm volatile("mov.b32 %0, %1;" : "=f"(acc[i]) : "f"(ac2[i]));
    }
    if (t128 == 0) TS(wg ? 16 : 6);
    {
      float tp[2] = {0.f, 0.f};
#pragma unroll
      for (int j = 0; j < 12; j++) {
        const float* a = &acc[8 * j];
        const float k3 = j < 2 ? GK3 : fmaf(tp[j & 1], 0.0f, GK3);
        float o[8];
#pragma unroll
        for (int e = 0; e < 8; e++) {
          float z = a[e] * fmaf(a[e] * k3, a[e], GK1);
          asm("tanh.approx.f32 %0, %0;" : "+f"(z));
          if (e == GDEP) tp[j & 1] = z;
          o[e] = fmaf(a[e], z, a[e]);
        }
        stmatrix4t(ad + j * 2048, and_or(pack_bf16(o[0], o[1]), uam, uom), pack_bf16(o[2], o[3]), and_or(pack_bf16(o[4], o[5]), uam, uom), pack_bf16(o[6], o[7]));
        if (j == 5) {
          fence_async_smem();
          bar_arrive(11 + wgu, 160);
        }
        if ((j == 5 && helper && !wgu) || (j == 9 && !helper)) break;
      }
      fence_async_smem();
      bar_arrive(13 + wgu, 160);
      if (t128 == 0) TS(wg ? 29 : 28);
    }
    if (g2) {
      const int mb = wgu ^ r;
      uint32_t gb[18];
      {
        float a0 = 0.f, a1 = 0.f;
        if (wgu) {
          a0 = __bfloat162float(p.b2[s2 + 64 * mb + 16 * w + g]); a1 = __bfloat162float(p.b2[s2 + 64 * mb + 16 * w + 8 + g]);
          int it = 0;
          uint32_t bad;
          do {
            bad = 0;
#pragma unroll
            for (int i = 0; i < 18; i++) {
              const uint2 v = ld_rlx2(sc->mod + 3 * D_ + d2 + 8 * i + 2 * t);
              bad |= (v.x ^ tag16) | (v.y ^ tag16);
              gb[i] = __byte_perm(v.x, v.y, 0x7632);
            }
          } while (any(bad & 0xffffu) && ++it < SPIN_MAX);
        }
#pragma unroll
        for (int i = 0; i < 72; i++) acc[i] = (i & 2) ? a1 : a0;
      }
      rg.st++;
      gemm_main<3>(acc, sb4 + mb * 512 + LA, 0, sb4 + 1024 + (1 << 16), wgu, rg, x1p, xr);
      if (t128 == 0) TS(wg ? 20 : 19);
      constexpr uint32_t sx = sbase + O_U1, so = sbase + XST * STAGE2;
      if (wgu == 0) {
        uint4* dst = sc->part + z2 * 1152 + t128;
#pragma unroll
        for (int j = 0; j < 9; j++) {
          const float* a = &acc[8 * j];
          dst[j * 128] = make_uint4(set_tag(pack_bf16(a[0], a[1]), tag1), pack_bf16(a[2], a[3]), pack_bf16(a[4], a[5]), pack_bf16(a[6], a[7]));
        }
        if (tid == 0) TS(21);
        const uint4* src = sc->part + (z2 ^ 64) * 1152 + t128;
        uint4 v[9];
        uint32_t bad;
        int it = 0;
        do {
#pragma unroll
          for (int j = 0; j < 9; j++) v[j] = ld_rlx4(src + j * 128);
          bad = or3(or3(diff2(v[0].x, v[1].x, tag1), diff2(v[2].x, v[3].x, tag1), diff2(v[4].x, v[5].x, tag1)), diff2(v[6].x, v[7].x, tag1), v[8].x ^ tag1);
        } while (any(bad & 1) && ++it < SPIN_MAX);
#pragma unroll
        for (int j = 0; j < 9; j++) sts4(sx + t128 * 16 + j * 2048, v[j].x, v[j].y, v[j].z, v[j].w);
        bar_arrive(2 + w, 64);
        if (tid == 0) TS(1);
        if (w == 0) {
#pragma unroll 1
          for (int i = 0; i < 3; i++) {
            bar_sync(11 + i, 160);
            if (elect()) tma_st2d(&maps.out, so + i * 6144, d2 + 48 * i, s2 + 64 * (r ^ 1));
            __syncwarp();
          }
          if (elect()) { bulk_commit_wait_read(); TS(22); }
          __syncwarp();
        }
      } else {
        mbar_wait(full0 + 8 * XST, rg.ph);
        bar_sync(2 + w, 64);
        if (t128 == 0) TS(5);
        if (tid == 128 && cta == 0) sc->cnt[C_EP] = ep;
        const uint32_t xa = so + (16 * w + (l & 15)) * 96 + (l >> 4) * 16;
#pragma unroll
        for (int c = 0; c < 3; c++) {
          uint32_t pv[3][4], xv[3][4];
#pragma unroll
          for (int j = 0; j < 3; j++) {
            asm volatile("ld.shared.v4.b32 {%0,%1,%2,%3}, [%4];" : "=r"(pv[j][0]), "=r"(pv[j][1]), "=r"(pv[j][2]), "=r"(pv[j][3]) : "r"(sx + t128 * 16 + (3 * c + j) * 2048) : "memory");
            asm volatile("ldmatrix.sync.aligned.m8n8.x4.shared.b16 {%0,%1,%2,%3}, [%4];" : "=r"(xv[j][0]), "=r"(xv[j][1]), "=r"(xv[j][2]), "=r"(xv[j][3]) : "r"(xa + c * 6144 + j * 32) : "memory");
          }
#pragma unroll
          for (int j = 0; j < 3; j++) {
            const float* a = &acc[8 * (3 * c + j)];
            uint32_t o[4];
#pragma unroll
            for (int e = 0; e < 4; e++)
              o[e] = hadd2(xv[j][e], hmul2(gb[2 * (3 * c + j) + (e >> 1)], pack_bf16(a[2 * e] + bf_lo(pv[j][e]), a[2 * e + 1] + bf_hi(pv[j][e]))));
            stmatrix4(xa + c * 6144 + j * 32, o[0], o[1], o[2], o[3]);
          }
          fence_async_smem();
          asm volatile("bar.arrive %0, 160;" ::"r"(11 + c) : "memory");
        }
        if (t128 == 0) TS(7);
        __syncwarp();
      }
    }
  }
}

typedef CUresult (*EncodeFn)(CUtensorMap*, CUtensorMapDataType, cuuint32_t, void*, const cuuint64_t*, const cuuint64_t*, const cuuint32_t*,
                             const cuuint32_t*, CUtensorMapInterleave, CUtensorMapSwizzle, CUtensorMapL2promotion, CUtensorMapFloatOOBfill);

struct Dim { cuuint64_t n, stride; cuuint32_t box; };
template <int RANK>
void make_map(EncodeFn enc, CUtensorMap* m, bool words, int swz, const void* ptr, const Dim (&d)[RANK]) {
  cuuint64_t gd[RANK], gs[RANK];
  cuuint32_t bx[RANK], es[RANK];
  for (int i = 0; i < RANK; i++) { gd[i] = d[i].n; gs[i] = d[i].stride; bx[i] = d[i].box; es[i] = 1; }
  enc(m, words ? CU_TENSOR_MAP_DATA_TYPE_UINT32 : CU_TENSOR_MAP_DATA_TYPE_BFLOAT16, RANK, const_cast<void*>(ptr), gd, gs + 1, bx, es,
      CU_TENSOR_MAP_INTERLEAVE_NONE, static_cast<CUtensorMapSwizzle>(swz),
      swz == 3 ? CU_TENSOR_MAP_L2_PROMOTION_L2_256B : CU_TENSOR_MAP_L2_PROMOTION_NONE, CU_TENSOR_MAP_FLOAT_OOB_FILL_NONE);
}

}

extern "C" void kernel_launch(void* const* d_in, const int* in_sizes, int n_in, void* d_out, int out_size) {
  (void)in_sizes; (void)n_in; (void)out_size;
  static EncodeFn enc = nullptr;
  static void *sptr = nullptr, *tptr = nullptr;
  if (!enc) {
    void* f = nullptr; cudaDriverEntryPointQueryResult qr;
    cudaGetDriverEntryPoint("cuTensorMapEncodeTiled", &f, cudaEnableDefault, &qr);
    enc = reinterpret_cast<EncodeFn>(f);
    cudaFuncSetAttribute(fused_kernel, cudaFuncAttributeMaxDynamicSharedMemorySize, SMEM_BYTES);
    cudaGetSymbolAddress(&sptr, g_s);
    cudaGetSymbolAddress(&tptr, T_TAB);
  }
  Params p;
  p.x = (const __nv_bfloat16*)d_in[0]; p.wr = (const __nv_bfloat16*)d_in[1]; p.wi = (const __nv_bfloat16*)d_in[2];
  p.b1 = (const __nv_bfloat16*)d_in[5]; p.b2 = (const __nv_bfloat16*)d_in[7];
  p.c = (const __nv_bfloat16*)d_in[8]; p.wmod = (const __nv_bfloat16*)d_in[9];
  p.w1 = (const __nv_bfloat16*)d_in[4]; p.w2 = (const __nv_bfloat16*)d_in[6];
  p.s = static_cast<Scratch*>(sptr); p.tab = static_cast<const uint4*>(tptr);
  Maps maps;
  make_map<4>(enc, &maps.w1a, false, 3, p.w1, {{64, 0, 64}, {16, 128 * 2 * F_, 4}, {128, 2 * F_, 16}, {72, 128, 2}});
  make_map<4>(enc, &maps.w1b, false, 3, p.w1, {{64, 0, 64}, {16, 128 * 2 * F_, 4}, {128, 2 * F_, 16}, {72, 128, 3}});
  make_map<3>(enc, &maps.w2, false, 3, p.w2, {{64, 0, 64}, {F_, 2 * S_, 64}, {32, 128, 2}});
  make_map<2>(enc, &maps.x1, false, 0, p.s->x1, {{D_, 0, 48}, {S_, 2 * D_, 64}});
  make_map<2>(enc, &maps.out, false, 0, d_out, {{D_, 0, 48}, {S_, 2 * D_, 64}});
  make_map<2>(enc, &maps.z1, true, 0, p.s->z1, {{5120, 0, 40}, {120, 20480, 60}});
  for (int i = 0; i < 2; i++) make_map<2>(enc, &maps.z2[i], true, 0, p.s->z2, {{4800, 0, i ? 16u : 24u}, {128, 19200, 128}});
  for (int i = 0; i < 4; i++) make_map<2>(enc, &maps.wf[i], false, 2 - (i & 1), (i & 2) ? p.wi : p.wr, {{16 * DF_, 0, (i & 1) ? 16u : 32u}, {128, 32 * DF_, 128}});
  make_map<2>(enc, &maps.wm, false, 1, p.wmod, {{6 * D_, 0, 16}, {D_, 12 * D_, 192}});
  for (int i = 0; i < 2; i++) make_map<3>(enc, &maps.h3[i], true, 0, p.s->h3, {{1024, 0, 64}, {144, 4096, 18}, {4, 144 * 4096, i ? 4u - H3G : H3G}});
  fused_kernel<<<NCTA, NTHR, SMEM_BYTES, cudaStreamPerThread>>>(p, maps);
}
```

```cpp
#include <cuda_runtime.h>
#include <cuda_bf16.h>
#include <cuda.h>
#include <stdint.h>

namespace {

constexpr int S_ = 2048, D_ = 576, DF_ = 289, F_ = 4608;
constexpr int NCTA = 132, NTHR = 384;
constexpr int STAGE = 36864, NST = 6;
constexpr int STAGE2 = 34816, O_U1 = NST * STAGE2, O_GB = O_U1 + 20480, SMEM_BYTES = 232448;
constexpr uint32_t sbase = 1024, red = sbase + NST * STAGE, full0 = sbase + SMEM_BYTES - 256, empty0 = full0 + 8 * NST;
constexpr int O_NRM = 0, O_B1 = 19456, O_Z1 = 38912, O_P2 = 59392, O_ST = 3 * STAGE;
constexpr int O_RAW = 4 * STAGE;
constexpr int O_IN = 4 * STAGE, O_Y = O_IN + 19456, O_B3 = O_IN + 38912, O_MOD = O_IN + 57344;

__device__ __align__(128) const uint32_t T_TAB[5632] = {
0x3f803f80,0xbf803f80,0x3f803f80,0xbf803f80,0x3f803f80,0xbf803f80,0x3f803f80,0xbf803f80,0x3f803f80,0xbf803f80,0x3f803f80,0xbf803f80,
0x3f803f80,0xbf803f80,0x3f803f80,0xbf803f80,0x3f7f3f80,0xbdc90000,0x3f223f35,0xbf46bf35,0x3f753f7b,0xbe95be48,0x3ef13f0e,0xbf62bf55,
0x3f623f6d,0xbef1bec4,0x3e953ec4,0xbf75bf6d,0x3f463f55,0xbf22bf0e,0x3dc93e48,0xbf7fbf7b,0x3f7b3f80,0xbe480000,0xbe480000,0xbf7bbf80,
0x3f553f6d,0xbf0ebec4,0xbf0ebec4,0xbf55bf6d,0x3f0e3f35,0xbf55bf35,0xbf55bf35,0xbf0ebf35,0x3e483ec4,0xbf7bbf6d,0xbf7bbf6d,0xbe48bec4,
0x3f753f80,0xbe950000,0xbf62bf35,0xbef1bf35,0x3f223f55,0xbf46bf0e,0xbf7fbf7b,0x3dc9be48,0x3dc93ec4,0xbf7fbf6d,0xbf46bf6d,0x3f223ec4,
0xbef1be48,0xbf62bf7b,0xbe95bf0e,0x3f753f55,0x3f6d3f80,0xbec40000,0xbf6dbf80,0x3ec40000,0x3ec43f35,0xbf6dbf35,0xbec4bf35,0x3f6d3f35,
0xbec40000,0xbf6dbf80,0x3ec40000,0x3f6d3f80,0xbf6dbf35,0xbec4bf35,0x3f6d3f35,0x3ec43f35,0x3f623f80,0xbef10000,0xbe95bf35,0x3f753f35,
0x3dc93f0e,0xbf7fbf55,0x3f223e48,0x3f463f7b,0xbf46bec4,0xbf22bf6d,0x3f7f3f6d,0xbdc93ec4,0xbf75bf7b,0x3e95be48,0x3ef13f55,0xbf62bf0e,
0x3f553f80,0xbf0e0000,0x3f0e0000,0x3f553f80,0xbe483ec4,0xbf7bbf6d,0x3f7b3f6d,0xbe483ec4,0xbf7bbf35,0xbe48bf35,0x3e483f35,0xbf7bbf35,
0xbf0ebf6d,0x3f553ec4,0xbf55bec4,0xbf0ebf6d,0x3f463f80,0xbf220000,0x3f7f3f35,0x3dc93f35,0xbef13e48,0xbf62bf7b,0x3e953f55,0xbf75bf0e,
0xbf75bf6d,0x3e95bec4,0xbf62bec4,0xbef1bf6d,0x3dc9bf0e,0x3f7f3f55,0xbf22bf7b,0x3f463e48,0x3f353f80,0xbf350000,0x3f353f80,0xbf350000,
0xbf350000,0xbf35bf80,0xbf350000,0xbf35bf80,0xbf35bf80,0x3f350000,0xbf35bf80,0x3f350000,0x3f350000,0x3f353f80,0x3f350000,0x3f353f80,
0x3f223f80,0xbf460000,0xbdc93f35,0xbf7fbf35,0xbf62be48,0xbef1bf7b,0xbf75bf55,0x3e95bf0e,0xbe95bf6d,0x3f753ec4,0x3ef1bec4,0x3f623f6d,
0x3f7f3f0e,0x3dc93f55,0x3f463f7b,0xbf223e48,0x3f0e3f80,0xbf550000,0xbf550000,0xbf0ebf80,0xbf7bbec4,0xbe48bf6d,0xbe48bf6d,0x3f7b3ec4,
0x3e48bf35,0x3f7b3f35,0x3f7b3f35,0xbe483f35,0x3f553f6d,0xbf0e3ec4,0xbf0e3ec4,0xbf55bf6d,0x3ef13f80,0xbf620000,0xbf75bf35,0x3e95bf35,
0xbf7fbf0e,0x3dc9bf55,0x3f46be48,0x3f223f7b,0x3f22bec4,0x3f463f6d,0x3dc93f6d,0xbf7fbec4,0x3e953f7b,0xbf75be48,0xbf62bf55,0x3ef1bf0e,
0x3ec43f80,0xbf6d0000,0xbec4bf80,0x3f6d0000,0xbf6dbf35,0x3ec4bf35,0x3f6d3f35,0xbec43f35,0x3f6d0000,0x3ec43f80,0xbf6d0000,0xbec4bf80,
0xbec43f35,0xbf6dbf35,0x3ec4bf35,0x3f6d3f35,0x3e953f80,0xbf750000,0x3ef1bf35,0x3f623f35,0xbf46bf55,0x3f22bf0e,0x3dc93f7b,0xbf7fbe48,
0x3f7f3ec4,0xbdc93f6d,0xbf22bf6d,0x3f46bec4,0xbf623e48,0xbef1bf7b,0x3f753f0e,0xbe953f55,0x3e483f80,0xbf7b0000,0x3f7b0000,0x3e483f80,
0xbf0ebf6d,0x3f55bec4,0xbf553ec4,0xbf0ebf6d,0x3f553f35,0xbf0e3f35,0x3f0ebf35,0x3f553f35,0xbf7bbec4,0x3e48bf6d,0xbe483f6d,0xbf7bbec4,
0x3dc93f80,0xbf7f0000,0x3f463f35,0xbf223f35,0xbe95bf7b,0x3f75be48,0xbf62bf0e,0x3ef1bf55,0x3ef13f6d,0xbf623ec4,0x3f753ec4,0xbe953f6d,
0xbf22bf55,0x3f46bf0e,0xbf7fbe48,0x3dc9bf7b,0x3f80,0xbf800000,0x3f80,0xbf800000,0xbf80,0x3f800000,0xbf80,0x3f800000,
0x3f80,0xbf800000,0x3f80,0xbf800000,0xbf80,0x3f800000,0xbf80,0x3f800000,0xbdc93f80,0xbf7f0000,0xbf463f35,0xbf22bf35,
0x3e95bf7b,0x3f753e48,0x3f62bf0e,0x3ef13f55,0xbef13f6d,0xbf62bec4,0xbf753ec4,0xbe95bf6d,0x3f22bf55,0x3f463f0e,0x3f7fbe48,0x3dc93f7b,
0xbe483f80,0xbf7b0000,0xbf7b0000,0x3e48bf80,0x3f0ebf6d,0x3f553ec4,0x3f553ec4,0xbf0e3f6d,0xbf553f35,0xbf0ebf35,0xbf0ebf35,0x3f55bf35,
0x3f7bbec4,0x3e483f6d,0x3e483f6d,0xbf7b3ec4,0xbe953f80,0xbf750000,0xbef1bf35,0x3f62bf35,0x3f46bf55,0x3f223f0e,0xbdc93f7b,0xbf7f3e48,
0xbf7f3ec4,0xbdc9bf6d,0x3f22bf6d,0x3f463ec4,0x3f623e48,0xbef13f7b,0xbf753f0e,0xbe95bf55,0xbec43f80,0xbf6d0000,0x3ec4bf80,0x3f6d0000,
0x3f6dbf35,0x3ec43f35,0xbf6d3f35,0xbec4bf35,0xbf6d0000,0x3ec4bf80,0x3f6d0000,0xbec43f80,0x3ec43f35,0xbf6d3f35,0xbec4bf35,0x3f6dbf35,
0xbef13f80,0xbf620000,0x3f75bf35,0x3e953f35,0x3f7fbf0e,0x3dc93f55,0xbf46be48,0x3f22bf7b,0xbf22bec4,0x3f46bf6d,0xbdc93f6d,0xbf7f3ec4,
0xbe953f7b,0xbf753e48,0x3f62bf55,0x3ef13f0e,0xbf0e3f80,0xbf550000,0x3f550000,0xbf0e3f80,0x3f7bbec4,0xbe483f6d,0x3e48bf6d,0x3f7bbec4,
0xbe48bf35,0x3f7bbf35,0xbf7b3f35,0xbe48bf35,0xbf553f6d,0xbf0ebec4,0x3f0e3ec4,0xbf553f6d,0xbf223f80,0xbf460000,0x3dc93f35,0xbf7f3f35,
0x3f62be48,0xbef13f7b,0x3f75bf55,0x3e953f0e,0x3e95bf6d,0x3f75bec4,0xbef1bec4,0x3f62bf6d,0xbf7f3f0e,0x3dc9bf55,0xbf463f7b,0xbf22be48,
0xbf353f80,0xbf350000,0xbf353f80,0xbf350000,0x3f350000,0xbf353f80,0x3f350000,0xbf353f80,0x3f35bf80,0x3f350000,0x3f35bf80,0x3f350000,
0xbf350000,0x3f35bf80,0xbf350000,0x3f35bf80,0xbf463f80,0xbf220000,0xbf7f3f35,0x3dc9bf35,0x3ef13e48,0xbf623f7b,0xbe953f55,0xbf753f0e,
0x3f75bf6d,0x3e953ec4,0x3f62bec4,0xbef13f6d,0xbdc9bf0e,0x3f7fbf55,0x3f22bf7b,0x3f46be48,0xbf553f80,0xbf0e0000,0xbf0e0000,0x3f55bf80,
0x3e483ec4,0xbf7b3f6d,0xbf7b3f6d,0xbe48bec4,0x3f7bbf35,0xbe483f35,0xbe483f35,0xbf7b3f35,0x3f0ebf6d,0x3f55bec4,0x3f55bec4,0xbf0e3f6d,
0xbf623f80,0xbef10000,0x3e95bf35,0x3f75bf35,0xbdc93f0e,0xbf7f3f55,0xbf223e48,0x3f46bf7b,0x3f46bec4,0xbf223f6d,0xbf7f3f6d,0xbdc9bec4,
0x3f75bf7b,0x3e953e48,0xbef13f55,0xbf623f0e,0xbf6d3f80,0xbec40000,0x3f6dbf80,0x3ec40000,0xbec43f35,0xbf6d3f35,0x3ec4bf35,0x3f6dbf35,
0x3ec40000,0xbf6d3f80,0xbec40000,0x3f6dbf80,0x3f6dbf35,0xbec43f35,0xbf6d3f35,0x3ec4bf35,0xbf753f80,0xbe950000,0x3f62bf35,0xbef13f35,
0xbf223f55,0xbf463f0e,0x3f7fbf7b,0x3dc93e48,0xbdc93ec4,0xbf7f3f6d,0x3f46bf6d,0x3f22bec4,0x3ef1be48,0xbf623f7b,0x3e95bf0e,0x3f75bf55,
0xbf7b3f80,0xbe480000,0x3e480000,0xbf7b3f80,0xbf553f6d,0xbf0e3ec4,0x3f0ebec4,0xbf553f6d,0xbf0e3f35,0xbf553f35,0x3f55bf35,0xbf0e3f35,
0xbe483ec4,0xbf7b3f6d,0x3f7bbf6d,0xbe483ec4,0xbf7f3f80,0xbdc90000,0xbf223f35,0xbf463f35,0xbf753f7b,0xbe953e48,0xbef13f0e,0xbf623f55,
0xbf623f6d,0xbef13ec4,0xbe953ec4,0xbf753f6d,0xbf463f55,0xbf223f0e,0xbdc93e48,0xbf7f3f7b,0x3f803f80,0xbf803f80,0x3f803f80,0xbf803f80,
0x3f803f80,0xbf803f80,0x3f803f80,0xbf803f80,0x3f803f80,0xbf803f80,0x3f803f80,0xbf803f80,0x3f803f80,0xbf803f80,0x3f803f80,0xbf803f80,
0xbdc90000,0xbf7fbf80,0xbf46bf35,0xbf22bf35,0xbe95be48,0xbf75bf7b,0xbf62bf55,0xbef1bf0e,0xbef1bec4,0xbf62bf6d,0xbf75bf6d,0xbe95bec4,
0xbf22bf0e,0xbf46bf55,0xbf7fbf7b,0xbdc9be48,0xbf7bbf80,0x3e480000,0x3e480000,0x3f7b3f80,0xbf55bf6d,0x3f0e3ec4,0x3f0e3ec4,0x3f553f6d,
0xbf0ebf35,0x3f553f35,0x3f553f35,0x3f0e3f35,0xbe48bec4,0x3f7b3f6d,0x3f7b3f6d,0x3e483ec4,0x3e950000,0x3f753f80,0x3ef13f35,0xbf62bf35,
0x3f463f0e,0x3f223f55,0xbdc93e48,0xbf7fbf7b,0x3f7f3f6d,0x3dc93ec4,0xbf22bec4,0xbf46bf6d,0x3f623f7b,0xbef1be48,0xbf75bf55,0xbe95bf0e,
0x3f6d3f80,0xbec40000,0xbf6dbf80,0x3ec40000,0x3ec43f35,0xbf6dbf35,0xbec4bf35,0x3f6d3f35,0xbec40000,0xbf6dbf80,0x3ec40000,0x3f6d3f80,
0xbf6dbf35,0xbec4bf35,0x3f6d3f35,0x3ec43f35,0xbef10000,0xbf62bf80,0x3f753f35,0x3e953f35,0xbf7fbf55,0xbdc9bf0e,0x3f463f7b,0xbf22be48,
0xbf22bf6d,0x3f463ec4,0xbdc93ec4,0xbf7fbf6d,0x3e95be48,0x3f753f7b,0xbf62bf0e,0xbef1bf55,0xbf55bf80,0x3f0e0000,0xbf0e0000,0xbf55bf80,
0x3e48bec4,0x3f7b3f6d,0xbf7bbf6d,0x3e48bec4,0x3f7b3f35,0x3e483f35,0xbe48bf35,0x3f7b3f35,0x3f0e3f6d,0xbf55bec4,0x3f553ec4,0x3f0e3f6d,
0x3f220000,0x3f463f80,0xbdc9bf35,0x3f7f3f35,0x3f623f7b,0xbef13e48,0x3f753f0e,0x3e953f55,0xbe953ec4,0xbf75bf6d,0x3ef13f6d,0xbf62bec4,
0xbf7fbf55,0x3dc9bf0e,0xbf46be48,0xbf22bf7b,0x3f353f80,0xbf350000,0x3f353f80,0xbf350000,0xbf350000,0xbf35bf80,0xbf350000,0xbf35bf80,
0xbf35bf80,0x3f350000,0xbf35bf80,0x3f350000,0x3f350000,0x3f353f80,0x3f350000,0x3f353f80,0xbf460000,0xbf22bf80,0xbf7fbf35,0x3dc9bf35,
0xbef1bf7b,0x3f623e48,0x3e95bf0e,0x3f753f55,0x3f753ec4,0x3e953f6d,0x3f623f6d,0xbef13ec4,0x3dc93f55,0xbf7fbf0e,0xbf223e48,0xbf46bf7b,
0xbf0ebf80,0x3f550000,0x3f550000,0x3f0e3f80,0x3f7b3ec4,0x3e483f6d,0x3e483f6d,0xbf7bbec4,0xbe483f35,0xbf7bbf35,0xbf7bbf35,0x3e48bf35,
0xbf55bf6d,0x3f0ebec4,0x3f0ebec4,0x3f553f6d,0x3f620000,0x3ef13f80,0xbe953f35,0xbf75bf35,0xbdc93f55,0xbf7fbf0e,0xbf22bf7b,0x3f46be48,
0xbf46bf6d,0x3f22bec4,0x3f7f3ec4,0x3dc93f6d,0x3f753e48,0x3e953f7b,0xbef13f0e,0xbf62bf55,0x3ec43f80,0xbf6d0000,0xbec4bf80,0x3f6d0000,
0xbf6dbf35,0x3ec4bf35,0x3f6d3f35,0xbec43f35,0x3f6d0000,0x3ec43f80,0xbf6d0000,0xbec4bf80,0xbec43f35,0xbf6dbf35,0x3ec4bf35,0x3f6d3f35,
0xbf750000,0xbe95bf80,0x3f623f35,0xbef13f35,0x3f22bf0e,0x3f463f55,0xbf7fbe48,0xbdc9bf7b,0xbdc93f6d,0xbf7fbec4,0x3f46bec4,0x3f223f6d,
0xbef1bf7b,0x3f62be48,0xbe953f55,0xbf75bf0e,0xbe48bf80,0x3f7b0000,0xbf7b0000,0xbe48bf80,0x3f0e3f6d,0xbf553ec4,0x3f55bec4,0x3f0e3f6d,
0xbf55bf35,0x3f0ebf35,0xbf0e3f35,0xbf55bf35,0x3f7b3ec4,0xbe483f6d,0x3e48bf6d,0x3f7b3ec4,0x3f7f0000,0x3dc93f80,0x3f22bf35,0x3f463f35,
0xbf753e48,0xbe95bf7b,0xbef13f55,0xbf62bf0e,0x3f62bec4,0x3ef13f6d,0x3e95bf6d,0x3f753ec4,0xbf463f0e,0xbf22bf55,0xbdc93f7b,0xbf7fbe48,
0x3f80,0xbf800000,0x3f80,0xbf800000,0xbf80,0x3f800000,0xbf80,0x3f800000,0x3f80,0xbf800000,0x3f80,0xbf800000,
0xbf80,0x3f800000,0xbf80,0x3f800000,0xbf7f0000,0x3dc9bf80,0xbf22bf35,0x3f46bf35,0x3f753e48,0xbe953f7b,0x3ef13f55,0xbf623f0e,
0xbf62bec4,0x3ef1bf6d,0xbe95bf6d,0x3f75bec4,0x3f463f0e,0xbf223f55,0x3dc93f7b,0xbf7f3e48,0x3e48bf80,0x3f7b0000,0x3f7b0000,0xbe483f80,
0xbf0e3f6d,0xbf55bec4,0xbf55bec4,0x3f0ebf6d,0x3f55bf35,0x3f0e3f35,0x3f0e3f35,0xbf553f35,0xbf7b3ec4,0xbe48bf6d,0xbe48bf6d,0x3f7bbec4,
0x3f750000,0xbe953f80,0xbf623f35,0xbef1bf35,0xbf22bf0e,0x3f46bf55,0x3f7fbe48,0xbdc93f7b,0x3dc93f6d,0xbf7f3ec4,0xbf46bec4,0x3f22bf6d,
0x3ef1bf7b,0x3f623e48,0x3e953f55,0xbf753f0e,0xbec43f80,0xbf6d0000,0x3ec4bf80,0x3f6d0000,0x3f6dbf35,0x3ec43f35,0xbf6d3f35,0xbec4bf35,
0xbf6d0000,0x3ec4bf80,0x3f6d0000,0xbec43f80,0x3ec43f35,0xbf6d3f35,0xbec4bf35,0x3f6dbf35,0xbf620000,0x3ef1bf80,0x3e953f35,0xbf753f35,
0x3dc93f55,0xbf7f3f0e,0x3f22bf7b,0x3f463e48,0x3f46bf6d,0x3f223ec4,0xbf7f3ec4,0x3dc9bf6d,0xbf753e48,0x3e95bf7b,0x3ef13f0e,0xbf623f55,
0x3f0ebf80,0x3f550000,0xbf550000,0x3f0ebf80,0xbf7b3ec4,0x3e48bf6d,0xbe483f6d,0xbf7b3ec4,0x3e483f35,0xbf7b3f35,0x3f7bbf35,0x3e483f35,
0x3f55bf6d,0x3f0e3ec4,0xbf0ebec4,0x3f55bf6d,0x3f460000,0xbf223f80,0x3f7fbf35,0x3dc93f35,0x3ef1bf7b,0x3f62be48,0xbe95bf0e,0x3f75bf55,
0xbf753ec4,0x3e95bf6d,0xbf623f6d,0xbef1bec4,0xbdc93f55,0xbf7f3f0e,0x3f223e48,0xbf463f7b,0xbf353f80,0xbf350000,0xbf353f80,0xbf350000,
0x3f350000,0xbf353f80,0x3f350000,0xbf353f80,0x3f35bf80,0x3f350000,0x3f35bf80,0x3f350000,0xbf350000,0x3f35bf80,0xbf350000,0x3f35bf80,
0xbf220000,0x3f46bf80,0x3dc9bf35,0x3f7fbf35,0xbf623f7b,0xbef1be48,0xbf753f0e,0x3e95bf55,0x3e953ec4,0xbf753f6d,0xbef13f6d,0xbf623ec4,
0x3f7fbf55,0x3dc93f0e,0x3f46be48,0xbf223f7b,0x3f55bf80,0x3f0e0000,0x3f0e0000,0xbf553f80,0xbe48bec4,0x3f7bbf6d,0x3f7bbf6d,0x3e483ec4,
0xbf7b3f35,0x3e48bf35,0x3e48bf35,0x3f7bbf35,0xbf0e3f6d,0xbf553ec4,0xbf553ec4,0x3f0ebf6d,0x3ef10000,0xbf623f80,0xbf753f35,0x3e95bf35,
0x3f7fbf55,0xbdc93f0e,0xbf463f7b,0xbf223e48,0x3f22bf6d,0x3f46bec4,0x3dc93ec4,0xbf7f3f6d,0xbe95be48,0x3f75bf7b,0x3f62bf0e,0xbef13f55,
0xbf6d3f80,0xbec40000,0x3f6dbf80,0x3ec40000,0xbec43f35,0xbf6d3f35,0x3ec4bf35,0x3f6dbf35,0x3ec40000,0xbf6d3f80,0xbec40000,0x3f6dbf80,
0x3f6dbf35,0xbec43f35,0xbf6d3f35,0x3ec4bf35,0xbe950000,0x3f75bf80,0xbef13f35,0xbf623f35,0xbf463f0e,0x3f22bf55,0x3dc93e48,0xbf7f3f7b,
0xbf7f3f6d,0x3dc9bec4,0x3f22bec4,0xbf463f6d,0xbf623f7b,0xbef13e48,0x3f75bf55,0xbe953f0e,0x3f7bbf80,0x3e480000,0xbe480000,0x3f7bbf80,
0x3f55bf6d,0x3f0ebec4,0xbf0e3ec4,0x3f55bf6d,0x3f0ebf35,0x3f55bf35,0xbf553f35,0x3f0ebf35,0x3e48bec4,0x3f7bbf6d,0xbf7b3f6d,0x3e48bec4,
0x3dc90000,0xbf7f3f80,0x3f46bf35,0xbf223f35,0x3e95be48,0xbf753f7b,0x3f62bf55,0xbef13f0e,0x3ef1bec4,0xbf623f6d,0x3f75bf6d,0xbe953ec4,
0x3f22bf0e,0xbf463f55,0x3f7fbf7b,0xbdc93e48,0x3f803f80,0xbf803f80,0x3f803f80,0xbf803f80,0x3f803f80,0xbf803f80,0x3f803f80,0xbf803f80,
0x3f803f80,0xbf803f80,0x3f803f80,0xbf803f80,0x3f803f80,0xbf803f80,0x3f803f80,0xbf803f80,0xbf7fbf80,0x3dc90000,0xbf22bf35,0x3f463f35,
0xbf75bf7b,0x3e953e48,0xbef1bf0e,0x3f623f55,0xbf62bf6d,0x3ef13ec4,0xbe95bec4,0x3f753f6d,0xbf46bf55,0x3f223f0e,0xbdc9be48,0x3f7f3f7b,
0x3f7b3f80,0xbe480000,0xbe480000,0xbf7bbf80,0x3f553f6d,0xbf0ebec4,0xbf0ebec4,0xbf55bf6d,0x3f0e3f35,0xbf55bf35,0xbf55bf35,0xbf0ebf35,
0x3e483ec4,0xbf7bbf6d,0xbf7bbf6d,0xbe48bec4,0xbf75bf80,0x3e950000,0x3f623f35,0x3ef13f35,0xbf22bf55,0x3f463f0e,0x3f7f3f7b,0xbdc93e48,
0xbdc9bec4,0x3f7f3f6d,0x3f463f6d,0xbf22bec4,0x3ef13e48,0x3f623f7b,0x3e953f0e,0xbf75bf55,0x3f6d3f80,0xbec40000,0xbf6dbf80,0x3ec40000,
0x3ec43f35,0xbf6dbf35,0xbec4bf35,0x3f6d3f35,0xbec40000,0xbf6dbf80,0x3ec40000,0x3f6d3f80,0xbf6dbf35,0xbec4bf35,0x3f6d3f35,0x3ec43f35,
0xbf62bf80,0x3ef10000,0x3e953f35,0xbf75bf35,0xbdc9bf0e,0x3f7f3f55,0xbf22be48,0xbf46bf7b,0x3f463ec4,0x3f223f6d,0xbf7fbf6d,0x3dc9bec4,
0x3f753f7b,0xbe953e48,0xbef1bf55,0x3f623f0e,0x3f553f80,0xbf0e0000,0x3f0e0000,0x3f553f80,0xbe483ec4,0xbf7bbf6d,0x3f7b3f6d,0xbe483ec4,
0xbf7bbf35,0xbe48bf35,0x3e483f35,0xbf7bbf35,0xbf0ebf6d,0x3f553ec4,0xbf55bec4,0xbf0ebf6d,0xbf46bf80,0x3f220000,0xbf7fbf35,0xbdc9bf35,
0x3ef1be48,0x3f623f7b,0xbe95bf55,0x3f753f0e,0x3f753f6d,0xbe953ec4,0x3f623ec4,0x3ef13f6d,0xbdc93f0e,0xbf7fbf55,0x3f223f7b,0xbf46be48,
0x3f353f80,0xbf350000,0x3f353f80,0xbf350000,0xbf350000,0xbf35bf80,0xbf350000,0xbf35bf80,0xbf35bf80,0x3f350000,0xbf35bf80,0x3f350000,
0x3f350000,0x3f353f80,0x3f350000,0x3f353f80,0xbf22bf80,0x3f460000,0x3dc9bf35,0x3f7f3f35,0x3f623e48,0x3ef13f7b,0x3f753f55,0xbe953f0e,
0x3e953f6d,0xbf75bec4,0xbef13ec4,0xbf62bf6d,0xbf7fbf0e,0xbdc9bf55,0xbf46bf7b,0x3f22be48,0x3f0e3f80,0xbf550000,0xbf550000,0xbf0ebf80,
0xbf7bbec4,0xbe48bf6d,0xbe48bf6d,0x3f7b3ec4,0x3e48bf35,0x3f7b3f35,0x3f7b3f35,0xbe483f35,0x3f553f6d,0xbf0e3ec4,0xbf0e3ec4,0xbf55bf6d,
0xbef1bf80,0x3f620000,0x3f753f35,0xbe953f35,0x3f7f3f0e,0xbdc93f55,0xbf463e48,0xbf22bf7b,0xbf223ec4,0xbf46bf6d,0xbdc9bf6d,0x3f7f3ec4,
0xbe95bf7b,0x3f753e48,0x3f623f55,0xbef13f0e,0x3ec43f80,0xbf6d0000,0xbec4bf80,0x3f6d0000,0xbf6dbf35,0x3ec4bf35,0x3f6d3f35,0xbec43f35,
0x3f6d0000,0x3ec43f80,0xbf6d0000,0xbec4bf80,0xbec43f35,0xbf6dbf35,0x3ec4bf35,0x3f6d3f35,0xbe95bf80,0x3f750000,0xbef13f35,0xbf62bf35,
0x3f463f55,0xbf223f0e,0xbdc9bf7b,0x3f7f3e48,0xbf7fbec4,0x3dc9bf6d,0x3f223f6d,0xbf463ec4,0x3f62be48,0x3ef13f7b,0xbf75bf0e,0x3e95bf55,
0x3e483f80,0xbf7b0000,0x3f7b0000,0x3e483f80,0xbf0ebf6d,0x3f55bec4,0xbf553ec4,0xbf0ebf6d,0x3f553f35,0xbf0e3f35,0x3f0ebf35,0x3f553f35,
0xbf7bbec4,0x3e48bf6d,0xbe483f6d,0xbf7bbec4,0xbdc9bf80,0x3f7f0000,0xbf46bf35,0x3f22bf35,0x3e953f7b,0xbf753e48,0x3f623f0e,0xbef13f55,
0xbef1bf6d,0x3f62bec4,0xbf75bec4,0x3e95bf6d,0x3f223f55,0xbf463f0e,0x3f7f3e48,0xbdc93f7b,0x3f80,0xbf800000,0x3f80,0xbf800000,
0xbf80,0x3f800000,0xbf80,0x3f800000,0x3f80,0xbf800000,0x3f80,0xbf800000,0xbf80,0x3f800000,0xbf80,0x3f800000,
0x3dc9bf80,0x3f7f0000,0x3f46bf35,0x3f223f35,0xbe953f7b,0xbf75be48,0xbf623f0e,0xbef1bf55,0x3ef1bf6d,0x3f623ec4,0x3f75bec4,0x3e953f6d,
0xbf223f55,0xbf46bf0e,0xbf7f3e48,0xbdc9bf7b,0xbe483f80,0xbf7b0000,0xbf7b0000,0x3e48bf80,0x3f0ebf6d,0x3f553ec4,0x3f553ec4,0xbf0e3f6d,
0xbf553f35,0xbf0ebf35,0xbf0ebf35,0x3f55bf35,0x3f7bbec4,0x3e483f6d,0x3e483f6d,0xbf7b3ec4,0x3e95bf80,0x3f750000,0x3ef13f35,0xbf623f35,
0xbf463f55,0xbf22bf0e,0x3dc9bf7b,0x3f7fbe48,0x3f7fbec4,0x3dc93f6d,0xbf223f6d,0xbf46bec4,0xbf62be48,0x3ef1bf7b,0x3f75bf0e,0x3e953f55,
0xbec43f80,0xbf6d0000,0x3ec4bf80,0x3f6d0000,0x3f6dbf35,0x3ec43f35,0xbf6d3f35,0xbec4bf35,0xbf6d0000,0x3ec4bf80,0x3f6d0000,0xbec43f80,
0x3ec43f35,0xbf6d3f35,0xbec4bf35,0x3f6dbf35,0x3ef1bf80,0x3f620000,0xbf753f35,0xbe95bf35,0xbf7f3f0e,0xbdc9bf55,0x3f463e48,0xbf223f7b,
0x3f223ec4,0xbf463f6d,0x3dc9bf6d,0x3f7fbec4,0x3e95bf7b,0x3f75be48,0xbf623f55,0xbef1bf0e,0xbf0e3f80,0xbf550000,0x3f550000,0xbf0e3f80,
0x3f7bbec4,0xbe483f6d,0x3e48bf6d,0x3f7bbec4,0xbe48bf35,0x3f7bbf35,0xbf7b3f35,0xbe48bf35,0xbf553f6d,0xbf0ebec4,0x3f0e3ec4,0xbf553f6d,
0x3f22bf80,0x3f460000,0xbdc9bf35,0x3f7fbf35,0xbf623e48,0x3ef1bf7b,0xbf753f55,0xbe95bf0e,0xbe953f6d,0xbf753ec4,0x3ef13ec4,0xbf623f6d,
0x3f7fbf0e,0xbdc93f55,0x3f46bf7b,0x3f223e48,0xbf353f80,0xbf350000,0xbf353f80,0xbf350000,0x3f350000,0xbf353f80,0x3f350000,0xbf353f80,
0x3f35bf80,0x3f350000,0x3f35bf80,0x3f350000,0xbf350000,0x3f35bf80,0xbf350000,0x3f35bf80,0x3f46bf80,0x3f220000,0x3f7fbf35,0xbdc93f35,
0xbef1be48,0x3f62bf7b,0x3e95bf55,0x3f75bf0e,0xbf753f6d,0xbe95bec4,0xbf623ec4,0x3ef1bf6d,0x3dc93f0e,0xbf7f3f55,0xbf223f7b,0xbf463e48,
0xbf553f80,0xbf0e0000,0xbf0e0000,0x3f55bf80,0x3e483ec4,0xbf7b3f6d,0xbf7b3f6d,0xbe48bec4,0x3f7bbf35,0xbe483f35,0xbe483f35,0xbf7b3f35,
0x3f0ebf6d,0x3f55bec4,0x3f55bec4,0xbf0e3f6d,0x3f62bf80,0x3ef10000,0xbe953f35,0xbf753f35,0x3dc9bf0e,0x3f7fbf55,0x3f22be48,0xbf463f7b,
0xbf463ec4,0x3f22bf6d,0x3f7fbf6d,0x3dc93ec4,0xbf753f7b,0xbe95be48,0x3ef1bf55,0x3f62bf0e,0xbf6d3f80,0xbec40000,0x3f6dbf80,0x3ec40000,
0xbec43f35,0xbf6d3f35,0x3ec4bf35,0x3f6dbf35,0x3ec40000,0xbf6d3f80,0xbec40000,0x3f6dbf80,0x3f6dbf35,0xbec43f35,0xbf6d3f35,0x3ec4bf35,
0x3f75bf80,0x3e950000,0xbf623f35,0x3ef1bf35,0x3f22bf55,0x3f46bf0e,0xbf7f3f7b,0xbdc9be48,0x3dc9bec4,0x3f7fbf6d,0xbf463f6d,0xbf223ec4,
0xbef13e48,0x3f62bf7b,0xbe953f0e,0xbf753f55,0xbf7b3f80,0xbe480000,0x3e480000,0xbf7b3f80,0xbf553f6d,0xbf0e3ec4,0x3f0ebec4,0xbf553f6d,
0xbf0e3f35,0xbf553f35,0x3f55bf35,0xbf0e3f35,0xbe483ec4,0xbf7b3f6d,0x3f7bbf6d,0xbe483ec4,0x3f7fbf80,0x3dc90000,0x3f22bf35,0x3f46bf35,
0x3f75bf7b,0x3e95be48,0x3ef1bf0e,0x3f62bf55,0x3f62bf6d,0x3ef1bec4,0x3e95bec4,0x3f75bf6d,0x3f46bf55,0x3f22bf0e,0x3dc9be48,0x3f7fbf7b,
0x3f803f80,0xbf803f80,0x3f803f80,0xbf803f80,0x3f803f80,0xbf803f80,0x3f803f80,0xbf803f80,0x3f803f80,0xbf803f80,0x3f803f80,0xbf803f80,
0x3f803f80,0xbf803f80,0x3f803f80,0xbf803f80,0x3dc90000,0x3f7f3f80,0x3f463f35,0x3f223f35,0x3e953e48,0x3f753f7b,0x3f623f55,0x3ef13f0e,
0x3ef13ec4,0x3f623f6d,0x3f753f6d,0x3e953ec4,0x3f223f0e,0x3f463f55,0x3f7f3f7b,0x3dc93e48,0xbf7bbf80,0x3e480000,0x3e480000,0x3f7b3f80,
0xbf55bf6d,0x3f0e3ec4,0x3f0e3ec4,0x3f553f6d,0xbf0ebf35,0x3f553f35,0x3f553f35,0x3f0e3f35,0xbe48bec4,0x3f7b3f6d,0x3f7b3f6d,0x3e483ec4,
0xbe950000,0xbf75bf80,0xbef1bf35,0x3f623f35,0xbf46bf0e,0xbf22bf55,0x3dc9be48,0x3f7f3f7b,0xbf7fbf6d,0xbdc9bec4,0x3f223ec4,0x3f463f6d,
0xbf62bf7b,0x3ef13e48,0x3f753f55,0x3e953f0e,0x3f6d3f80,0xbec40000,0xbf6dbf80,0x3ec40000,0x3ec43f35,0xbf6dbf35,0xbec4bf35,0x3f6d3f35,
0xbec40000,0xbf6dbf80,0x3ec40000,0x3f6d3f80,0xbf6dbf35,0xbec4bf35,0x3f6d3f35,0x3ec43f35,0x3ef10000,0x3f623f80,0xbf75bf35,0xbe95bf35,
0x3f7f3f55,0x3dc93f0e,0xbf46bf7b,0x3f223e48,0x3f223f6d,0xbf46bec4,0x3dc9bec4,0x3f7f3f6d,0xbe953e48,0xbf75bf7b,0x3f623f0e,0x3ef13f55,
0xbf55bf80,0x3f0e0000,0xbf0e0000,0xbf55bf80,0x3e48bec4,0x3f7b3f6d,0xbf7bbf6d,0x3e48bec4,0x3f7b3f35,0x3e483f35,0xbe48bf35,0x3f7b3f35,
0x3f0e3f6d,0xbf55bec4,0x3f553ec4,0x3f0e3f6d,0xbf220000,0xbf46bf80,0x3dc93f35,0xbf7fbf35,0xbf62bf7b,0x3ef1be48,0xbf75bf0e,0xbe95bf55,
0x3e95bec4,0x3f753f6d,0xbef1bf6d,0x3f623ec4,0x3f7f3f55,0xbdc93f0e,0x3f463e48,0x3f223f7b,0x3f353f80,0xbf350000,0x3f353f80,0xbf350000,
0xbf350000,0xbf35bf80,0xbf350000,0xbf35bf80,0xbf35bf80,0x3f350000,0xbf35bf80,0x3f350000,0x3f350000,0x3f353f80,0x3f350000,0x3f353f80,
0x3f460000,0x3f223f80,0x3f7f3f35,0xbdc93f35,0x3ef13f7b,0xbf62be48,0xbe953f0e,0xbf75bf55,0xbf75bec4,0xbe95bf6d,0xbf62bf6d,0x3ef1bec4,
0xbdc9bf55,0x3f7f3f0e,0x3f22be48,0x3f463f7b,0xbf0ebf80,0x3f550000,0x3f550000,0x3f0e3f80,0x3f7b3ec4,0x3e483f6d,0x3e483f6d,0xbf7bbec4,
0xbe483f35,0xbf7bbf35,0xbf7bbf35,0x3e48bf35,0xbf55bf6d,0x3f0ebec4,0x3f0ebec4,0x3f553f6d,0xbf620000,0xbef1bf80,0x3e95bf35,0x3f753f35,
0x3dc9bf55,0x3f7f3f0e,0x3f223f7b,0xbf463e48,0x3f463f6d,0xbf223ec4,0xbf7fbec4,0xbdc9bf6d,0xbf75be48,0xbe95bf7b,0x3ef1bf0e,0x3f623f55,
0x3ec43f80,0xbf6d0000,0xbec4bf80,0x3f6d0000,0xbf6dbf35,0x3ec4bf35,0x3f6d3f35,0xbec43f35,0x3f6d0000,0x3ec43f80,0xbf6d0000,0xbec4bf80,
0xbec43f35,0xbf6dbf35,0x3ec4bf35,0x3f6d3f35,0x3f750000,0x3e953f80,0xbf62bf35,0x3ef1bf35,0xbf223f0e,0xbf46bf55,0x3f7f3e48,0x3dc93f7b,
0x3dc9bf6d,0x3f7f3ec4,0xbf463ec4,0xbf22bf6d,0x3ef13f7b,0xbf623e48,0x3e95bf55,0x3f753f0e,0xbe48bf80,0x3f7b0000,0xbf7b0000,0xbe48bf80,
0x3f0e3f6d,0xbf553ec4,0x3f55bec4,0x3f0e3f6d,0xbf55bf35,0x3f0ebf35,0xbf0e3f35,0xbf55bf35,0x3f7b3ec4,0xbe483f6d,0x3e48bf6d,0x3f7b3ec4,
0xbf7f0000,0xbdc9bf80,0xbf223f35,0xbf46bf35,0x3f75be48,0x3e953f7b,0x3ef1bf55,0x3f623f0e,0xbf623ec4,0xbef1bf6d,0xbe953f6d,0xbf75bec4,
0x3f46bf0e,0x3f223f55,0x3dc9bf7b,0x3f7f3e48,0x3f80,0xbf800000,0x3f80,0xbf800000,0xbf80,0x3f800000,0xbf80,0x3f800000,
0x3f80,0xbf800000,0x3f80,0xbf800000,0xbf80,0x3f800000,0xbf80,0x3f800000,0x3f7f0000,0xbdc93f80,0x3f223f35,0xbf463f35,
0xbf75be48,0x3e95bf7b,0xbef1bf55,0x3f62bf0e,0x3f623ec4,0xbef13f6d,0x3e953f6d,0xbf753ec4,0xbf46bf0e,0x3f22bf55,0xbdc9bf7b,0x3f7fbe48,
0x3e48bf80,0x3f7b0000,0x3f7b0000,0xbe483f80,0xbf0e3f6d,0xbf55bec4,0xbf55bec4,0x3f0ebf6d,0x3f55bf35,0x3f0e3f35,0x3f0e3f35,0xbf553f35,
0xbf7b3ec4,0xbe48bf6d,0xbe48bf6d,0x3f7bbec4,0xbf750000,0x3e95bf80,0x3f62bf35,0x3ef13f35,0x3f223f0e,0xbf463f55,0xbf7f3e48,0x3dc9bf7b,
0xbdc9bf6d,0x3f7fbec4,0x3f463ec4,0xbf223f6d,0xbef13f7b,0xbf62be48,0xbe95bf55,0x3f75bf0e,0xbec43f80,0xbf6d0000,0x3ec4bf80,0x3f6d0000,
0x3f6dbf35,0x3ec43f35,0xbf6d3f35,0xbec4bf35,0xbf6d0000,0x3ec4bf80,0x3f6d0000,0xbec43f80,0x3ec43f35,0xbf6d3f35,0xbec4bf35,0x3f6dbf35,
0x3f620000,0xbef13f80,0xbe95bf35,0x3f75bf35,0xbdc9bf55,0x3f7fbf0e,0xbf223f7b,0xbf46be48,0xbf463f6d,0xbf22bec4,0x3f7fbec4,0xbdc93f6d,
0x3f75be48,0xbe953f7b,0xbef1bf0e,0x3f62bf55,0x3f0ebf80,0x3f550000,0xbf550000,0x3f0ebf80,0xbf7b3ec4,0x3e48bf6d,0xbe483f6d,0xbf7b3ec4,
0x3e483f35,0xbf7b3f35,0x3f7bbf35,0x3e483f35,0x3f55bf6d,0x3f0e3ec4,0xbf0ebec4,0x3f55bf6d,0xbf460000,0x3f22bf80,0xbf7f3f35,0xbdc9bf35,
0xbef13f7b,0xbf623e48,0x3e953f0e,0xbf753f55,0x3f75bec4,0xbe953f6d,0x3f62bf6d,0x3ef13ec4,0x3dc9bf55,0x3f7fbf0e,0xbf22be48,0x3f46bf7b,
0xbf353f80,0xbf350000,0xbf353f80,0xbf350000,0x3f350000,0xbf353f80,0x3f350000,0xbf353f80,0x3f35bf80,0x3f350000,0x3f35bf80,0x3f350000,
0xbf350000,0x3f35bf80,0xbf350000,0x3f35bf80,0x3f220000,0xbf463f80,0xbdc93f35,0xbf7f3f35,0x3f62bf7b,0x3ef13e48,0x3f75bf0e,0xbe953f55,
0xbe95bec4,0x3f75bf6d,0x3ef1bf6d,0x3f62bec4,0xbf7f3f55,0xbdc9bf0e,0xbf463e48,0x3f22bf7b,0x3f55bf80,0x3f0e0000,0x3f0e0000,0xbf553f80,
0xbe48bec4,0x3f7bbf6d,0x3f7bbf6d,0x3e483ec4,0xbf7b3f35,0x3e48bf35,0x3e48bf35,0x3f7bbf35,0xbf0e3f6d,0xbf553ec4,0xbf553ec4,0x3f0ebf6d,
0xbef10000,0x3f62bf80,0x3f75bf35,0xbe953f35,0xbf7f3f55,0x3dc9bf0e,0x3f46bf7b,0x3f22be48,0xbf223f6d,0xbf463ec4,0xbdc9bec4,0x3f7fbf6d,
0x3e953e48,0xbf753f7b,0xbf623f0e,0x3ef1bf55,0xbf6d3f80,0xbec40000,0x3f6dbf80,0x3ec40000,0xbec43f35,0xbf6d3f35,0x3ec4bf35,0x3f6dbf35,
0x3ec40000,0xbf6d3f80,0xbec40000,0x3f6dbf80,0x3f6dbf35,0xbec43f35,0xbf6d3f35,0x3ec4bf35,0x3e950000,0xbf753f80,0x3ef1bf35,0x3f62bf35,
0x3f46bf0e,0xbf223f55,0xbdc9be48,0x3f7fbf7b,0x3f7fbf6d,0xbdc93ec4,0xbf223ec4,0x3f46bf6d,0x3f62bf7b,0x3ef1be48,0xbf753f55,0x3e95bf0e,
0x3f7bbf80,0x3e480000,0xbe480000,0x3f7bbf80,0x3f55bf6d,0x3f0ebec4,0xbf0e3ec4,0x3f55bf6d,0x3f0ebf35,0x3f55bf35,0xbf553f35,0x3f0ebf35,
0x3e48bec4,0x3f7bbf6d,0xbf7b3f6d,0x3e48bec4,0xbdc90000,0x3f7fbf80,0xbf463f35,0x3f22bf35,0xbe953e48,0x3f75bf7b,0xbf623f55,0x3ef1bf0e,
0xbef13ec4,0x3f62bf6d,0xbf753f6d,0x3e95bec4,0xbf223f0e,0x3f46bf55,0xbf7f3f7b,0x3dc9be48,0x40003f80,0x3fb53f80,0x3f80,0xbfb53f80,
0x40004000,0xbfb50000,0x0,0xbfb5c000,0x40004000,0xbfb5c000,0x0,0x3fb50000,0x40004000,0x3fb50000,0x0,0x3fb54000,
0x3fff3f80,0x3fa23f80,0xbe49bf80,0xbfc6bf80,0x3ff53ffb,0xbfe2bec8,0xbf15bec8,0xbf71bffb,0x3fe23fed,0xbf15bfed,0xbf71bf44,0x3ff53f44,
0x3fc63fd5,0x3fff3f8e,0xbfa2bf8e,0x3e493fd5,0x3ffb3f80,0x3f8e3f80,0xbec83f80,0xbfd53f80,0x3fd53fed,0xbffbbf44,0xbf8ebf44,0xbec8bfed,
0x3f8e3fb5,0x3ec8bfb5,0xbfd5bfb5,0x3ffb3fb5,0x3ec83f44,0x3fd53fed,0xbffbbfed,0xbf8e3f44,0x3ff53f80,0x3f713f80,0xbf15bf80,0xbfe2bf80,
0x3fa23fd5,0xbfffbf8e,0xbfc6bf8e,0x3e49bfd5,0x3e493f44,0x3fa2bf44,0xbfffbfed,0x3fc63fed,0xbf71bec8,0x3f153ffb,0xbfe2bffb,0xbff5bec8,
0x3fed3f80,0x3f443f80,0xbf443f80,0xbfed3f80,0x3f443fb5,0xbfedbfb5,0xbfedbfb5,0x3f44bfb5,0xbf440000,0x3fed0000,0xbfedc000,0x3f444000,
0xbfedbfb5,0xbf443fb5,0xbf44bfb5,0xbfedbfb5,0x3fe23f80,0x3f153f80,0xbf71bf80,0xbff5bf80,0x3e493f8e,0xbfc6bfd5,0xbfffbfd5,0x3fa2bf8e,
0xbfc6bf44,0x3fff3f44,0xbfa2bfed,0xbe493fed,0xbff5bffb,0xbfe23ec8,0x3f15bec8,0xbf71bffb,0x3fd53f80,0x3ec83f80,0xbf8e3f80,0xbffb3f80,
0xbec83f44,0xbf8ebfed,0xbffbbfed,0x3fd5bf44,0xbffbbfb5,0x3fd53fb5,0xbec8bfb5,0xbf8e3fb5,0xbf8ebfed,0xbffbbf44,0x3fd53f44,0x3ec8bfed,
0x3fc63f80,0x3e493f80,0xbfa2bf80,0xbfffbf80,0xbf713ec8,0xbf15bffb,0xbfe2bffb,0x3ff5bec8,0xbff5bfed,0x3f713fed,0x3f15bf44,0xbfe23f44,
0x3e49bf8e,0xbfa2bfd5,0x3fff3fd5,0x3fc6bf8e,0x3f80,0xbfb53f80,0xc0003f80,0xbfb53f80,0xc000,0x3fb50000,0x40000000,0xbfb54000,
0x4000,0x3fb5c000,0xc0000000,0x3fb50000,0xc000,0xbfb50000,0x40000000,0x3fb5c000,0xbe493f80,0xbfc63f80,0xbfffbf80,0xbfa2bf80,
0x3f15bffb,0x3f713ec8,0x3ff53ec8,0xbfe23ffb,0xbf713fed,0x3ff5bfed,0xbfe2bf44,0x3f153f44,0x3fa2bfd5,0xbe49bf8e,0x3fc63f8e,0x3fffbfd5,
0xbec83f80,0xbfd53f80,0xbffb3f80,0xbf8e3f80,0x3f8ebfed,0x3ec83f44,0x3fd53f44,0xbffb3fed,0xbfd53fb5,0x3ffbbfb5,0xbf8ebfb5,0xbec83fb5,
0x3ffbbf44,0x3f8ebfed,0x3ec83fed,0x3fd5bf44,0xbf153f80,0xbfe23f80,0xbff5bf80,0xbf71bf80,0x3fc6bfd5,0xbe493f8e,0x3fa23f8e,0xbfff3fd5,
0xbfff3f44,0x3fc6bf44,0xbe49bfed,0xbfa23fed,0x3fe23ec8,0x3ff5bffb,0xbf713ffb,0x3f153ec8,0xbf443f80,0xbfed3f80,0xbfed3f80,0xbf443f80,
0x3fedbfb5,0xbf443fb5,0x3f443fb5,0xbfed3fb5,0xbfed0000,0x3f440000,0x3f44c000,0xbfed4000,0x3f443fb5,0x3fedbfb5,0xbfed3fb5,0xbf443fb5,
0xbf713f80,0xbff53f80,0xbfe2bf80,0xbf15bf80,0x3fffbf8e,0xbfa23fd5,0x3e493fd5,0xbfc63f8e,0xbfa2bf44,0xbe493f44,0x3fc6bfed,0xbfff3fed,
0xbf153ffb,0x3f71bec8,0xbff53ec8,0xbfe23ffb,0xbf8e3f80,0xbffb3f80,0xbfd53f80,0xbec83f80,0x3ffbbf44,0xbfd53fed,0xbec83fed,0xbf8e3f44,
0xbec8bfb5,0xbf8e3fb5,0x3ffbbfb5,0xbfd53fb5,0xbfd53fed,0xbec83f44,0xbf8ebf44,0xbffb3fed,0xbfa23f80,0xbfff3f80,0xbfc6bf80,0xbe49bf80,
0x3fe2bec8,0xbff53ffb,0xbf713ffb,0xbf153ec8,0x3f15bfed,0xbfe23fed,0x3ff5bf44,0xbf713f44,0xbfff3f8e,0xbfc63fd5,0x3e49bfd5,0xbfa23f8e,
0xc0003f80,0xbfb53f80,0x3f80,0x3fb53f80,0xc0004000,0x3fb50000,0x0,0x3fb5c000,0xc0004000,0x3fb5c000,0x0,0xbfb50000,
0xc0004000,0xbfb50000,0x0,0xbfb54000,0xbfff3f80,0xbfa23f80,0x3e49bf80,0x3fc6bf80,0xbff53ffb,0x3fe2bec8,0x3f15bec8,0x3f71bffb,
0xbfe23fed,0x3f15bfed,0x3f71bf44,0xbff53f44,0xbfc63fd5,0xbfff3f8e,0x3fa2bf8e,0xbe493fd5,0xbffb3f80,0xbf8e3f80,0x3ec83f80,0x3fd53f80,
0xbfd53fed,0x3ffbbf44,0x3f8ebf44,0x3ec8bfed,0xbf8e3fb5,0xbec8bfb5,0x3fd5bfb5,0xbffb3fb5,0xbec83f44,0xbfd53fed,0x3ffbbfed,0x3f8e3f44,
0xbff53f80,0xbf713f80,0x3f15bf80,0x3fe2bf80,0xbfa23fd5,0x3fffbf8e,0x3fc6bf8e,0xbe49bfd5,0xbe493f44,0xbfa2bf44,0x3fffbfed,0xbfc63fed,
0x3f71bec8,0xbf153ffb,0x3fe2bffb,0x3ff5bec8,0xbfed3f80,0xbf443f80,0x3f443f80,0x3fed3f80,0xbf443fb5,0x3fedbfb5,0x3fedbfb5,0xbf44bfb5,
0x3f440000,0xbfed0000,0x3fedc000,0xbf444000,0x3fedbfb5,0x3f443fb5,0x3f44bfb5,0x3fedbfb5,0xbfe23f80,0xbf153f80,0x3f71bf80,0x3ff5bf80,
0xbe493f8e,0x3fc6bfd5,0x3fffbfd5,0xbfa2bf8e,0x3fc6bf44,0xbfff3f44,0x3fa2bfed,0x3e493fed,0x3ff5bffb,0x3fe23ec8,0xbf15bec8,0x3f71bffb,
0xbfd53f80,0xbec83f80,0x3f8e3f80,0x3ffb3f80,0x3ec83f44,0x3f8ebfed,0x3ffbbfed,0xbfd5bf44,0x3ffbbfb5,0xbfd53fb5,0x3ec8bfb5,0x3f8e3fb5,
0x3f8ebfed,0x3ffbbf44,0xbfd53f44,0xbec8bfed,0xbfc63f80,0xbe493f80,0x3fa2bf80,0x3fffbf80,0x3f713ec8,0x3f15bffb,0x3fe2bffb,0xbff5bec8,
0x3ff5bfed,0xbf713fed,0xbf15bf44,0x3fe23f44,0xbe49bf8e,0x3fa2bfd5,0xbfff3fd5,0xbfc6bf8e,0x3f80,0x3fb53f80,0x40003f80,0x3fb53f80,
0xc000,0xbfb50000,0xc0000000,0x3fb54000,0x4000,0xbfb5c000,0x40000000,0xbfb50000,0xc000,0x3fb50000,0xc0000000,0xbfb5c000,
0x3e493f80,0x3fc63f80,0x3fffbf80,0x3fa2bf80,0xbf15bffb,0xbf713ec8,0xbff53ec8,0x3fe23ffb,0x3f713fed,0xbff5bfed,0x3fe2bf44,0xbf153f44,
0xbfa2bfd5,0x3e49bf8e,0xbfc63f8e,0xbfffbfd5,0x3ec83f80,0x3fd53f80,0x3ffb3f80,0x3f8e3f80,0xbf8ebfed,0xbec83f44,0xbfd53f44,0x3ffb3fed,
0x3fd53fb5,0xbffbbfb5,0x3f8ebfb5,0x3ec83fb5,0xbffbbf44,0xbf8ebfed,0xbec83fed,0xbfd5bf44,0x3f153f80,0x3fe23f80,0x3ff5bf80,0x3f71bf80,
0xbfc6bfd5,0x3e493f8e,0xbfa23f8e,0x3fff3fd5,0x3fff3f44,0xbfc6bf44,0x3e49bfed,0x3fa23fed,0xbfe23ec8,0xbff5bffb,0x3f713ffb,0xbf153ec8,
0x3f443f80,0x3fed3f80,0x3fed3f80,0x3f443f80,0xbfedbfb5,0x3f443fb5,0xbf443fb5,0x3fed3fb5,0x3fed0000,0xbf440000,0xbf44c000,0x3fed4000,
0xbf443fb5,0xbfedbfb5,0x3fed3fb5,0x3f443fb5,0x3f713f80,0x3ff53f80,0x3fe2bf80,0x3f15bf80,0xbfffbf8e,0x3fa23fd5,0xbe493fd5,0x3fc63f8e,
0x3fa2bf44,0x3e493f44,0xbfc6bfed,0x3fff3fed,0x3f153ffb,0xbf71bec8,0x3ff53ec8,0x3fe23ffb,0x3f8e3f80,0x3ffb3f80,0x3fd53f80,0x3ec83f80,
0xbffbbf44,0x3fd53fed,0x3ec83fed,0x3f8e3f44,0x3ec8bfb5,0x3f8e3fb5,0xbffbbfb5,0x3fd53fb5,0x3fd53fed,0x3ec83f44,0x3f8ebf44,0x3ffb3fed,
0x3fa23f80,0x3fff3f80,0x3fc6bf80,0x3e49bf80,0xbfe2bec8,0x3ff53ffb,0x3f713ffb,0x3f153ec8,0xbf15bfed,0x3fe23fed,0xbff5bf44,0x3f713f44,
0x3fff3f8e,0x3fc63fd5,0xbe49bfd5,0x3fa23f8e,0x40004000,0x3fb54000,0x0,0xbfb50000,0x40004000,0xbfb50000,0x0,0xbfb5c000,
0x40004000,0xbfb5c000,0x0,0x3fb50000,0x40004000,0x3fb50000,0x0,0x3fb54000,0x3fa23fb5,0xbe493fb5,0xbfc6bfb5,0xbfffbfb5,
0x3f713f8e,0xbff5bfd5,0xbfe2bfd5,0x3f15bf8e,0x3f153f44,0x3f71bf44,0xbff5bfed,0x3fe23fed,0x3e493ec8,0x3fc63ffb,0xbfffbffb,0xbfa23ec8,
0xbec80000,0xbfd50000,0xbffbc000,0xbf8ec000,0xbf8ebf44,0xbec8bfed,0xbfd5bfed,0x3ffb3f44,0xbfd5bfb5,0x3ffb3fb5,0xbf8ebfb5,0xbec83fb5,
0xbffbbfed,0xbf8e3f44,0xbec8bf44,0xbfd5bfed,0xbfe2bfb5,0xbff5bfb5,0xbf71bfb5,0x3f15bfb5,0xbfffbffb,0x3fc6bec8,0x3e49bec8,0x3fa23ffb,
0xbfc6bfed,0x3e493fed,0x3fa23f44,0xbfffbf44,0xbf15bf8e,0xbfe2bfd5,0x3ff53fd5,0x3f71bf8e,0xbfedc000,0xbf44c000,0x3f440000,0x3fed0000,
0xbf44bfb5,0x3fed3fb5,0x3fed3fb5,0xbf443fb5,0x3f440000,0xbfed0000,0x3fed4000,0xbf44c000,0x3fed3fb5,0x3f44bfb5,0x3f443fb5,0x3fed3fb5,
0xbf15bfb5,0x3f71bfb5,0x3ff53fb5,0x3fe23fb5,0x3fa23ec8,0x3e493ffb,0x3fc63ffb,0xbfffbec8,0x3fff3fed,0xbfa2bfed,0xbe493f44,0x3fc6bf44,
0x3f713fd5,0x3ff53f8e,0xbfe2bf8e,0xbf153fd5,0x3f8e0000,0x3ffb0000,0x3fd54000,0x3ec84000,0x3ffb3fed,0xbfd53f44,0xbec83f44,0xbf8ebfed,
0x3ec83fb5,0x3f8ebfb5,0xbffbbfb5,0x3fd53fb5,0xbfd5bf44,0xbec83fed,0xbf8ebfed,0xbffbbf44,0x3fff3fb5,0x3fc63fb5,0x3e493fb5,0xbfa23fb5,
0x3f153fd5,0xbfe2bf8e,0xbff5bf8e,0x3f71bfd5,0xbfe2bf44,0x3ff53f44,0xbf71bfed,0xbf153fed,0xbfa2bffb,0xbfffbec8,0x3fc63ec8,0x3e49bffb,
0x4000,0xbfb54000,0xc0000000,0xbfb50000,0xc000,0x3fb50000,0x40000000,0xbfb54000,0x4000,0x3fb5c000,0xc0000000,0x3fb50000,
0xc000,0xbfb50000,0x40000000,0x3fb5c000,0xbfc63fb5,0xbfff3fb5,0xbfa2bfb5,0x3e49bfb5,0x3fe2bf8e,0xbf153fd5,0x3f713fd5,0xbff53f8e,
0xbff53f44,0x3fe2bf44,0xbf15bfed,0xbf713fed,0x3fffbec8,0x3fa2bffb,0x3e493ffb,0x3fc6bec8,0xbffb0000,0xbf8e0000,0x3ec8c000,0x3fd5c000,
0x3fd53f44,0xbffb3fed,0xbf8e3fed,0xbec8bf44,0xbf8ebfb5,0xbec83fb5,0x3fd5bfb5,0xbffb3fb5,0x3ec83fed,0x3fd5bf44,0xbffb3f44,0xbf8e3fed,
0xbf71bfb5,0x3f15bfb5,0x3fe2bfb5,0x3ff5bfb5,0xbe493ffb,0xbfa23ec8,0xbfff3ec8,0x3fc6bffb,0x3fa2bfed,0xbfff3fed,0x3fc63f44,0xbe49bf44,
0xbff53f8e,0xbf713fd5,0xbf15bfd5,0xbfe23f8e,0x3f44c000,0x3fedc000,0x3fed0000,0x3f440000,0xbfed3fb5,0x3f44bfb5,0xbf44bfb5,0x3fedbfb5,
0x3fed0000,0xbf440000,0xbf444000,0x3fedc000,0xbf44bfb5,0xbfed3fb5,0x3fedbfb5,0x3f44bfb5,0x3ff5bfb5,0x3fe2bfb5,0x3f153fb5,0xbf713fb5,
0xbfc6bec8,0x3fffbffb,0x3fa2bffb,0x3e493ec8,0xbe493fed,0x3fc6bfed,0xbfff3f44,0x3fa2bf44,0x3fe2bfd5,0x3f15bf8e,0x3f713f8e,0x3ff5bfd5,
0x3fd50000,0x3ec80000,0xbf8e4000,0xbffb4000,0x3ec8bfed,0x3f8ebf44,0x3ffbbf44,0xbfd53fed,0xbffb3fb5,0x3fd5bfb5,0xbec8bfb5,0xbf8e3fb5,
0x3f8e3f44,0x3ffbbfed,0xbfd53fed,0xbec83f44,0x3e493fb5,0xbfa23fb5,0xbfff3fb5,0xbfc63fb5,0x3ff5bfd5,0xbf713f8e,0x3f153f8e,0xbfe23fd5,
0xbf71bf44,0xbf153f44,0x3fe2bfed,0xbff53fed,0xbfc63ffb,0xbe493ec8,0xbfa2bec8,0xbfff3ffb,0xc0004000,0xbfb54000,0x0,0x3fb50000,
0xc0004000,0x3fb50000,0x0,0x3fb5c000,0xc0004000,0x3fb5c000,0x0,0xbfb50000,0xc0004000,0xbfb50000,0x0,0xbfb54000,
0xbfa23fb5,0x3e493fb5,0x3fc6bfb5,0x3fffbfb5,0xbf713f8e,0x3ff5bfd5,0x3fe2bfd5,0xbf15bf8e,0xbf153f44,0xbf71bf44,0x3ff5bfed,0xbfe23fed,
0xbe493ec8,0xbfc63ffb,0x3fffbffb,0x3fa23ec8,0x3ec80000,0x3fd50000,0x3ffbc000,0x3f8ec000,0x3f8ebf44,0x3ec8bfed,0x3fd5bfed,0xbffb3f44,
0x3fd5bfb5,0xbffb3fb5,0x3f8ebfb5,0x3ec83fb5,0x3ffbbfed,0x3f8e3f44,0x3ec8bf44,0x3fd5bfed,0x3fe2bfb5,0x3ff5bfb5,0x3f71bfb5,0xbf15bfb5,
0x3fffbffb,0xbfc6bec8,0xbe49bec8,0xbfa23ffb,0x3fc6bfed,0xbe493fed,0xbfa23f44,0x3fffbf44,0x3f15bf8e,0x3fe2bfd5,0xbff53fd5,0xbf71bf8e,
0x3fedc000,0x3f44c000,0xbf440000,0xbfed0000,0x3f44bfb5,0xbfed3fb5,0xbfed3fb5,0x3f443fb5,0xbf440000,0x3fed0000,0xbfed4000,0x3f44c000,
0xbfed3fb5,0xbf44bfb5,0xbf443fb5,0xbfed3fb5,0x3f15bfb5,0xbf71bfb5,0xbff53fb5,0xbfe23fb5,0xbfa23ec8,0xbe493ffb,0xbfc63ffb,0x3fffbec8,
0xbfff3fed,0x3fa2bfed,0x3e493f44,0xbfc6bf44,0xbf713fd5,0xbff53f8e,0x3fe2bf8e,0x3f153fd5,0xbf8e0000,0xbffb0000,0xbfd54000,0xbec84000,
0xbffb3fed,0x3fd53f44,0x3ec83f44,0x3f8ebfed,0xbec83fb5,0xbf8ebfb5,0x3ffbbfb5,0xbfd53fb5,0x3fd5bf44,0x3ec83fed,0x3f8ebfed,0x3ffbbf44,
0xbfff3fb5,0xbfc63fb5,0xbe493fb5,0x3fa23fb5,0xbf153fd5,0x3fe2bf8e,0x3ff5bf8e,0xbf71bfd5,0x3fe2bf44,0xbff53f44,0x3f71bfed,0x3f153fed,
0x3fa2bffb,0x3fffbec8,0xbfc63ec8,0xbe49bffb,0x4000,0x3fb54000,0x40000000,0x3fb50000,0xc000,0xbfb50000,0xc0000000,0x3fb54000,
0x4000,0xbfb5c000,0x40000000,0xbfb50000,0xc000,0x3fb50000,0xc0000000,0xbfb5c000,0x3fc63fb5,0x3fff3fb5,0x3fa2bfb5,0xbe49bfb5,
0xbfe2bf8e,0x3f153fd5,0xbf713fd5,0x3ff53f8e,0x3ff53f44,0xbfe2bf44,0x3f15bfed,0x3f713fed,0xbfffbec8,0xbfa2bffb,0xbe493ffb,0xbfc6bec8,
0x3ffb0000,0x3f8e0000,0xbec8c000,0xbfd5c000,0xbfd53f44,0x3ffb3fed,0x3f8e3fed,0x3ec8bf44,0x3f8ebfb5,0x3ec83fb5,0xbfd5bfb5,0x3ffb3fb5,
0xbec83fed,0xbfd5bf44,0x3ffb3f44,0x3f8e3fed,0x3f71bfb5,0xbf15bfb5,0xbfe2bfb5,0xbff5bfb5,0x3e493ffb,0x3fa23ec8,0x3fff3ec8,0xbfc6bffb,
0xbfa2bfed,0x3fff3fed,0xbfc63f44,0x3e49bf44,0x3ff53f8e,0x3f713fd5,0x3f15bfd5,0x3fe23f8e,0xbf44c000,0xbfedc000,0xbfed0000,0xbf440000,
0x3fed3fb5,0xbf44bfb5,0x3f44bfb5,0xbfedbfb5,0xbfed0000,0x3f440000,0x3f444000,0xbfedc000,0x3f44bfb5,0x3fed3fb5,0xbfedbfb5,0xbf44bfb5,
0xbff5bfb5,0xbfe2bfb5,0xbf153fb5,0x3f713fb5,0x3fc6bec8,0xbfffbffb,0xbfa2bffb,0xbe493ec8,0x3e493fed,0xbfc6bfed,0x3fff3f44,0xbfa2bf44,
0xbfe2bfd5,0xbf15bf8e,0xbf713f8e,0xbff5bfd5,0xbfd50000,0xbec80000,0x3f8e4000,0x3ffb4000,0xbec8bfed,0xbf8ebf44,0xbffbbf44,0x3fd53fed,
0x3ffb3fb5,0xbfd5bfb5,0x3ec8bfb5,0x3f8e3fb5,0xbf8e3f44,0xbffbbfed,0x3fd53fed,0x3ec83f44,0xbe493fb5,0x3fa23fb5,0x3fff3fb5,0x3fc63fb5,
0xbff5bfd5,0x3f713f8e,0xbf153f8e,0x3fe23fd5,0x3f71bf44,0x3f153f44,0xbfe2bfed,0x3ff53fed,0x3fc63ffb,0x3e493ec8,0x3fa2bec8,0x3fff3ffb,
0x40004000,0x3fb54000,0x0,0xbfb50000,0x40004000,0xbfb50000,0x0,0xbfb5c000,0x40004000,0xbfb5c000,0x0,0x3fb50000,
0x40004000,0x3fb50000,0x0,0x3fb54000,0xbe490000,0xbfc60000,0xbfffc000,0xbfa2c000,0xbf15bec8,0xbf71bffb,0xbff5bffb,0x3fe23ec8,
0xbf71bf44,0x3ff53f44,0xbfe2bfed,0x3f153fed,0xbfa2bf8e,0x3e493fd5,0xbfc6bfd5,0xbfffbf8e,0xbffbc000,0xbf8ec000,0x3ec80000,0x3fd50000,
0xbfd5bfed,0x3ffb3f44,0x3f8e3f44,0x3ec83fed,0xbf8ebfb5,0xbec83fb5,0x3fd53fb5,0xbffbbfb5,0xbec8bf44,0xbfd5bfed,0x3ffb3fed,0x3f8ebf44,
0x3f150000,0x3fe20000,0x3ff54000,0x3f714000,0x3fc63f8e,0xbe493fd5,0x3fa23fd5,0xbfffbf8e,0x3fff3fed,0xbfc6bfed,0x3e493f44,0x3fa2bf44,
0x3fe23ffb,0x3ff53ec8,0xbf71bec8,0x3f153ffb,0x3fed4000,0x3f444000,0xbf440000,0xbfed0000,0x3f443fb5,0xbfedbfb5,0xbfedbfb5,0x3f44bfb5,
0xbf440000,0x3fed0000,0xbfedc000,0x3f444000,0xbfedbfb5,0xbf443fb5,0xbf44bfb5,0xbfedbfb5,0xbf710000,0xbff50000,0xbfe2c000,0xbf15c000,
0xbfffbfd5,0x3fa2bf8e,0xbe49bf8e,0x3fc63fd5,0xbfa2bfed,0xbe493fed,0x3fc63f44,0xbfffbf44,0x3f15bec8,0xbf71bffb,0x3ff53ffb,0x3fe2bec8,
0xbfd5c000,0xbec8c000,0x3f8e0000,0x3ffb0000,0x3ec8bf44,0x3f8e3fed,0x3ffb3fed,0xbfd53f44,0x3ffb3fb5,0xbfd5bfb5,0x3ec83fb5,0x3f8ebfb5,
0x3f8e3fed,0x3ffb3f44,0xbfd5bf44,0xbec83fed,0x3fa20000,0x3fff0000,0x3fc64000,0x3e494000,0x3fe23ffb,0xbff53ec8,0xbf713ec8,0xbf15bffb,
0xbf153f44,0x3fe2bf44,0xbff5bfed,0x3f713fed,0xbfffbfd5,0xbfc63f8e,0x3e49bf8e,0xbfa2bfd5,0x4000,0xbfb54000,0xc0000000,0xbfb50000,
0xc000,0x3fb50000,0x40000000,0xbfb54000,0x4000,0x3fb5c000,0xc0000000,0x3fb50000,0xc000,0xbfb50000,0x40000000,0x3fb5c000,
0xbfff0000,0xbfa20000,0x3e49c000,0x3fc6c000,0x3ff53ec8,0xbfe23ffb,0xbf153ffb,0xbf71bec8,0xbfe2bf44,0x3f153f44,0x3f71bfed,0xbff53fed,
0x3fc63f8e,0x3fffbfd5,0xbfa23fd5,0x3e493f8e,0x3ec8c000,0x3fd5c000,0x3ffb0000,0x3f8e0000,0xbf8e3fed,0xbec8bf44,0xbfd5bf44,0x3ffbbfed,
0x3fd5bfb5,0xbffb3fb5,0x3f8e3fb5,0x3ec8bfb5,0xbffb3f44,0xbf8e3fed,0xbec8bfed,0xbfd53f44,0x3ff50000,0x3f710000,0xbf154000,0xbfe24000,
0xbfa2bf8e,0x3fffbfd5,0x3fc6bfd5,0xbe493f8e,0x3e493fed,0x3fa2bfed,0xbfff3f44,0x3fc6bf44,0x3f71bffb,0xbf15bec8,0x3fe23ec8,0x3ff5bffb,
0xbf444000,0xbfed4000,0xbfed0000,0xbf440000,0x3fedbfb5,0xbf443fb5,0x3f443fb5,0xbfed3fb5,0xbfed0000,0x3f440000,0x3f44c000,0xbfed4000,
0x3f443fb5,0x3fedbfb5,0xbfed3fb5,0xbf443fb5,0xbfe20000,0xbf150000,0x3f71c000,0x3ff5c000,0x3e493fd5,0xbfc63f8e,0xbfff3f8e,0x3fa2bfd5,
0x3fc6bfed,0xbfff3fed,0x3fa23f44,0x3e49bf44,0xbff53ec8,0xbfe23ffb,0x3f15bffb,0xbf713ec8,0x3f8ec000,0x3ffbc000,0x3fd50000,0x3ec80000,
0xbffb3f44,0x3fd5bfed,0x3ec8bfed,0x3f8ebf44,0x3ec83fb5,0x3f8ebfb5,0xbffb3fb5,0x3fd5bfb5,0x3fd5bfed,0x3ec8bf44,0x3f8e3f44,0x3ffbbfed,
0x3fc60000,0x3e490000,0xbfa24000,0xbfff4000,0x3f71bffb,0x3f15bec8,0x3fe2bec8,0xbff53ffb,0xbff53f44,0x3f71bf44,0x3f15bfed,0xbfe23fed,
0xbe493fd5,0x3fa2bf8e,0xbfff3f8e,0xbfc63fd5,0xc0004000,0xbfb54000,0x0,0x3fb50000,0xc0004000,0x3fb50000,0x0,0x3fb5c000,
0xc0004000,0x3fb5c000,0x0,0xbfb50000,0xc0004000,0xbfb50000,0x0,0xbfb54000,0x3e490000,0x3fc60000,0x3fffc000,0x3fa2c000,
0x3f15bec8,0x3f71bffb,0x3ff5bffb,0xbfe23ec8,0x3f71bf44,0xbff53f44,0x3fe2bfed,0xbf153fed,0x3fa2bf8e,0xbe493fd5,0x3fc6bfd5,0x3fffbf8e,
0x3ffbc000,0x3f8ec000,0xbec80000,0xbfd50000,0x3fd5bfed,0xbffb3f44,0xbf8e3f44,0xbec83fed,0x3f8ebfb5,0x3ec83fb5,0xbfd53fb5,0x3ffbbfb5,
0x3ec8bf44,0x3fd5bfed,0xbffb3fed,0xbf8ebf44,0xbf150000,0xbfe20000,0xbff54000,0xbf714000,0xbfc63f8e,0x3e493fd5,0xbfa23fd5,0x3fffbf8e,
0xbfff3fed,0x3fc6bfed,0xbe493f44,0xbfa2bf44,0xbfe23ffb,0xbff53ec8,0x3f71bec8,0xbf153ffb,0xbfed4000,0xbf444000,0x3f440000,0x3fed0000,
0xbf443fb5,0x3fedbfb5,0x3fedbfb5,0xbf44bfb5,0x3f440000,0xbfed0000,0x3fedc000,0xbf444000,0x3fedbfb5,0x3f443fb5,0x3f44bfb5,0x3fedbfb5,
0x3f710000,0x3ff50000,0x3fe2c000,0x3f15c000,0x3fffbfd5,0xbfa2bf8e,0x3e49bf8e,0xbfc63fd5,0x3fa2bfed,0x3e493fed,0xbfc63f44,0x3fffbf44,
0xbf15bec8,0x3f71bffb,0xbff53ffb,0xbfe2bec8,0x3fd5c000,0x3ec8c000,0xbf8e0000,0xbffb0000,0xbec8bf44,0xbf8e3fed,0xbffb3fed,0x3fd53f44,
0xbffb3fb5,0x3fd5bfb5,0xbec83fb5,0xbf8ebfb5,0xbf8e3fed,0xbffb3f44,0x3fd5bf44,0x3ec83fed,0xbfa20000,0xbfff0000,0xbfc64000,0xbe494000,
0xbfe23ffb,0x3ff53ec8,0x3f713ec8,0x3f15bffb,0x3f153f44,0xbfe2bf44,0x3ff5bfed,0xbf713fed,0x3fffbfd5,0x3fc63f8e,0xbe49bf8e,0x3fa2bfd5,
0x4000,0x3fb54000,0x40000000,0x3fb50000,0xc000,0xbfb50000,0xc0000000,0x3fb54000,0x4000,0xbfb5c000,0x40000000,0xbfb50000,
0xc000,0x3fb50000,0xc0000000,0xbfb5c000,0x3fff0000,0x3fa20000,0xbe49c000,0xbfc6c000,0xbff53ec8,0x3fe23ffb,0x3f153ffb,0x3f71bec8,
0x3fe2bf44,0xbf153f44,0xbf71bfed,0x3ff53fed,0xbfc63f8e,0xbfffbfd5,0x3fa23fd5,0xbe493f8e,0xbec8c000,0xbfd5c000,0xbffb0000,0xbf8e0000,
0x3f8e3fed,0x3ec8bf44,0x3fd5bf44,0xbffbbfed,0xbfd5bfb5,0x3ffb3fb5,0xbf8e3fb5,0xbec8bfb5,0x3ffb3f44,0x3f8e3fed,0x3ec8bfed,0x3fd53f44,
0xbff50000,0xbf710000,0x3f154000,0x3fe24000,0x3fa2bf8e,0xbfffbfd5,0xbfc6bfd5,0x3e493f8e,0xbe493fed,0xbfa2bfed,0x3fff3f44,0xbfc6bf44,
0xbf71bffb,0x3f15bec8,0xbfe23ec8,0xbff5bffb,0x3f444000,0x3fed4000,0x3fed0000,0x3f440000,0xbfedbfb5,0x3f443fb5,0xbf443fb5,0x3fed3fb5,
0x3fed0000,0xbf440000,0xbf44c000,0x3fed4000,0xbf443fb5,0xbfedbfb5,0x3fed3fb5,0x3f443fb5,0x3fe20000,0x3f150000,0xbf71c000,0xbff5c000,
0xbe493fd5,0x3fc63f8e,0x3fff3f8e,0xbfa2bfd5,0xbfc6bfed,0x3fff3fed,0xbfa23f44,0xbe49bf44,0x3ff53ec8,0x3fe23ffb,0xbf15bffb,0x3f713ec8,
0xbf8ec000,0xbffbc000,0xbfd50000,0xbec80000,0x3ffb3f44,0xbfd5bfed,0xbec8bfed,0xbf8ebf44,0xbec83fb5,0xbf8ebfb5,0x3ffb3fb5,0xbfd5bfb5,
0xbfd5bfed,0xbec8bf44,0xbf8e3f44,0xbffbbfed,0xbfc60000,0xbe490000,0x3fa24000,0x3fff4000,0xbf71bffb,0xbf15bec8,0xbfe2bec8,0x3ff53ffb,
0x3ff53f44,0xbf71bf44,0xbf15bfed,0x3fe23fed,0x3e493fd5,0xbfa2bf8e,0x3fff3f8e,0x3fc63fd5,0x40004000,0x3fb54000,0x0,0xbfb50000,
0x40004000,0xbfb50000,0x0,0xbfb5c000,0x40004000,0xbfb5c000,0x0,0x3fb50000,0x40004000,0x3fb50000,0x0,0x3fb54000,
0xbfc6bfb5,0xbfffbfb5,0xbfa2bfb5,0x3e49bfb5,0xbfe2bfd5,0x3f15bf8e,0xbf71bf8e,0x3ff53fd5,0xbff5bfed,0x3fe23fed,0xbf15bf44,0xbf713f44,
0xbfffbffb,0xbfa23ec8,0xbe49bec8,0xbfc6bffb,0x3ec80000,0x3fd50000,0x3ffb4000,0x3f8e4000,0x3f8e3f44,0x3ec83fed,0x3fd53fed,0xbffbbf44,
0x3fd53fb5,0xbffbbfb5,0x3f8e3fb5,0x3ec8bfb5,0x3ffb3fed,0x3f8ebf44,0x3ec83f44,0x3fd53fed,0x3f713fb5,0xbf153fb5,0xbfe2bfb5,0xbff5bfb5,
0xbe493ec8,0xbfa2bffb,0xbfffbffb,0x3fc6bec8,0xbfa2bf44,0x3fff3f44,0xbfc6bfed,0x3e493fed,0xbff5bfd5,0xbf713f8e,0xbf15bf8e,0xbfe2bfd5,
0xbfedc000,0xbf44c000,0x3f440000,0x3fed0000,0xbf44bfb5,0x3fed3fb5,0x3fed3fb5,0xbf443fb5,0x3f440000,0xbfed0000,0x3fed4000,0xbf44c000,
0x3fed3fb5,0x3f44bfb5,0x3f443fb5,0x3fed3fb5,0x3ff53fb5,0x3fe23fb5,0x3f153fb5,0xbf713fb5,0x3fc63ffb,0xbfffbec8,0xbfa2bec8,0xbe49bffb,
0xbe493f44,0x3fc6bf44,0xbfffbfed,0x3fa23fed,0xbfe2bf8e,0xbf153fd5,0xbf71bfd5,0xbff5bf8e,0xbf8e0000,0xbffb0000,0xbfd5c000,0xbec8c000,
0xbffbbfed,0x3fd5bf44,0x3ec8bf44,0x3f8e3fed,0xbec8bfb5,0xbf8e3fb5,0x3ffb3fb5,0xbfd5bfb5,0x3fd53f44,0x3ec8bfed,0x3f8e3fed,0x3ffb3f44,
0xbe49bfb5,0x3fa2bfb5,0x3fff3fb5,0x3fc63fb5,0x3ff53f8e,0xbf713fd5,0x3f153fd5,0xbfe2bf8e,0x3f713fed,0x3f15bfed,0xbfe2bf44,0x3ff53f44,
0xbfc6bec8,0xbe493ffb,0xbfa2bffb,0xbfffbec8,0x4000,0xbfb54000,0xc0000000,0xbfb50000,0xc000,0x3fb50000,0x40000000,0xbfb54000,
0x4000,0x3fb5c000,0xc0000000,0x3fb50000,0xc000,0xbfb50000,0x40000000,0x3fb5c000,0xbfa2bfb5,0x3e49bfb5,0x3fc6bfb5,0x3fffbfb5,
0x3f713fd5,0xbff53f8e,0xbfe23f8e,0x3f15bfd5,0xbf15bfed,0xbf713fed,0x3ff5bf44,0xbfe23f44,0x3e493ffb,0x3fc6bec8,0xbfff3ec8,0xbfa23ffb,
0x3ffb0000,0x3f8e0000,0xbec84000,0xbfd54000,0xbfd5bf44,0x3ffbbfed,0x3f8ebfed,0x3ec83f44,0x3f8e3fb5,0x3ec8bfb5,0xbfd53fb5,0x3ffbbfb5,
0xbec8bfed,0xbfd53f44,0x3ffbbf44,0x3f8ebfed,0xbfe23fb5,0xbff53fb5,0xbf71bfb5,0x3f15bfb5,0x3fffbec8,0xbfc63ffb,0xbe493ffb,0xbfa23ec8,
0xbfc6bf44,0x3e493f44,0x3fa2bfed,0xbfff3fed,0x3f153fd5,0x3fe2bf8e,0xbff53f8e,0xbf713fd5,0x3f44c000,0x3fedc000,0x3fed0000,0x3f440000,
0xbfed3fb5,0x3f44bfb5,0xbf44bfb5,0x3fedbfb5,0x3fed0000,0xbf440000,0xbf444000,0x3fedc000,0xbf44bfb5,0xbfed3fb5,0x3fedbfb5,0x3f44bfb5,
0x3f153fb5,0xbf713fb5,0xbff53fb5,0xbfe23fb5,0x3fa2bffb,0x3e493ec8,0x3fc63ec8,0xbfff3ffb,0xbfff3f44,0x3fa2bf44,0x3e49bfed,0xbfc63fed,
0x3f713f8e,0x3ff5bfd5,0xbfe23fd5,0xbf153f8e,0xbfd50000,0xbec80000,0x3f8ec000,0x3ffbc000,0xbec83fed,0xbf8e3f44,0xbffb3f44,0x3fd5bfed,
0x3ffbbfb5,0xbfd53fb5,0x3ec83fb5,0x3f8ebfb5,0xbf8ebf44,0xbffb3fed,0x3fd5bfed,0x3ec8bf44,0x3fffbfb5,0x3fc6bfb5,0x3e493fb5,0xbfa23fb5,
0xbf15bf8e,0x3fe2bfd5,0x3ff5bfd5,0xbf713f8e,0xbfe23fed,0x3ff5bfed,0xbf71bf44,0xbf153f44,0x3fa23ec8,0x3fffbffb,0xbfc63ffb,0xbe493ec8,
0xc0004000,0xbfb54000,0x0,0x3fb50000,0xc0004000,0x3fb50000,0x0,0x3fb5c000,0xc0004000,0x3fb5c000,0x0,0xbfb50000,
0xc0004000,0xbfb50000,0x0,0xbfb54000,0x3fc6bfb5,0x3fffbfb5,0x3fa2bfb5,0xbe49bfb5,0x3fe2bfd5,0xbf15bf8e,0x3f71bf8e,0xbff53fd5,
0x3ff5bfed,0xbfe23fed,0x3f15bf44,0x3f713f44,0x3fffbffb,0x3fa23ec8,0x3e49bec8,0x3fc6bffb,0xbec80000,0xbfd50000,0xbffb4000,0xbf8e4000,
0xbf8e3f44,0xbec83fed,0xbfd53fed,0x3ffbbf44,0xbfd53fb5,0x3ffbbfb5,0xbf8e3fb5,0xbec8bfb5,0xbffb3fed,0xbf8ebf44,0xbec83f44,0xbfd53fed,
0xbf713fb5,0x3f153fb5,0x3fe2bfb5,0x3ff5bfb5,0x3e493ec8,0x3fa2bffb,0x3fffbffb,0xbfc6bec8,0x3fa2bf44,0xbfff3f44,0x3fc6bfed,0xbe493fed,
0x3ff5bfd5,0x3f713f8e,0x3f15bf8e,0x3fe2bfd5,0x3fedc000,0x3f44c000,0xbf440000,0xbfed0000,0x3f44bfb5,0xbfed3fb5,0xbfed3fb5,0x3f443fb5,
0xbf440000,0x3fed0000,0xbfed4000,0x3f44c000,0xbfed3fb5,0xbf44bfb5,0xbf443fb5,0xbfed3fb5,0xbff53fb5,0xbfe23fb5,0xbf153fb5,0x3f713fb5,
0xbfc63ffb,0x3fffbec8,0x3fa2bec8,0x3e49bffb,0x3e493f44,0xbfc6bf44,0x3fffbfed,0xbfa23fed,0x3fe2bf8e,0x3f153fd5,0x3f71bfd5,0x3ff5bf8e,
0x3f8e0000,0x3ffb0000,0x3fd5c000,0x3ec8c000,0x3ffbbfed,0xbfd5bf44,0xbec8bf44,0xbf8e3fed,0x3ec8bfb5,0x3f8e3fb5,0xbffb3fb5,0x3fd5bfb5,
0xbfd53f44,0xbec8bfed,0xbf8e3fed,0xbffb3f44,0x3e49bfb5,0xbfa2bfb5,0xbfff3fb5,0xbfc63fb5,0xbff53f8e,0x3f713fd5,0xbf153fd5,0x3fe2bf8e,
0xbf713fed,0xbf15bfed,0x3fe2bf44,0xbff53f44,0x3fc6bec8,0x3e493ffb,0x3fa2bffb,0x3fffbec8,0x4000,0x3fb54000,0x40000000,0x3fb50000,
0xc000,0xbfb50000,0xc0000000,0x3fb54000,0x4000,0xbfb5c000,0x40000000,0xbfb50000,0xc000,0x3fb50000,0xc0000000,0xbfb5c000,
0x3fa2bfb5,0xbe49bfb5,0xbfc6bfb5,0xbfffbfb5,0xbf713fd5,0x3ff53f8e,0x3fe23f8e,0xbf15bfd5,0x3f15bfed,0x3f713fed,0xbff5bf44,0x3fe23f44,
0xbe493ffb,0xbfc6bec8,0x3fff3ec8,0x3fa23ffb,0xbffb0000,0xbf8e0000,0x3ec84000,0x3fd54000,0x3fd5bf44,0xbffbbfed,0xbf8ebfed,0xbec83f44,
0xbf8e3fb5,0xbec8bfb5,0x3fd53fb5,0xbffbbfb5,0x3ec8bfed,0x3fd53f44,0xbffbbf44,0xbf8ebfed,0x3fe23fb5,0x3ff53fb5,0x3f71bfb5,0xbf15bfb5,
0xbfffbec8,0x3fc63ffb,0x3e493ffb,0x3fa23ec8,0x3fc6bf44,0xbe493f44,0xbfa2bfed,0x3fff3fed,0xbf153fd5,0xbfe2bf8e,0x3ff53f8e,0x3f713fd5,
0xbf44c000,0xbfedc000,0xbfed0000,0xbf440000,0x3fed3fb5,0xbf44bfb5,0x3f44bfb5,0xbfedbfb5,0xbfed0000,0x3f440000,0x3f444000,0xbfedc000,
0x3f44bfb5,0x3fed3fb5,0xbfedbfb5,0xbf44bfb5,0xbf153fb5,0x3f713fb5,0x3ff53fb5,0x3fe23fb5,0xbfa2bffb,0xbe493ec8,0xbfc63ec8,0x3fff3ffb,
0x3fff3f44,0xbfa2bf44,0xbe49bfed,0x3fc63fed,0xbf713f8e,0xbff5bfd5,0x3fe23fd5,0x3f153f8e,0x3fd50000,0x3ec80000,0xbf8ec000,0xbffbc000,
0x3ec83fed,0x3f8e3f44,0x3ffb3f44,0xbfd5bfed,0xbffbbfb5,0x3fd53fb5,0xbec83fb5,0xbf8ebfb5,0x3f8ebf44,0x3ffb3fed,0xbfd5bfed,0xbec8bf44,
0xbfffbfb5,0xbfc6bfb5,0xbe493fb5,0x3fa23fb5,0x3f15bf8e,0xbfe2bfd5,0xbff5bfd5,0x3f713f8e,0x3fe23fed,0xbff5bfed,0x3f71bf44,0x3f153f44,
0xbfa23ec8,0xbfffbffb,0x3fc63ffb,0x3e493ec8,0x80003f80,0x3f800000,0x80003f80,0x3f800000,0x80003f80,0x3f800000,0x80003f80,0x3f800000,
0x80003f80,0x3f800000,0x80003f80,0x3f800000,0x80003f80,0x3f800000,0x80003f80,0x3f800000,0x80003f80,0x3f800000,0x8000bf80,0xbf800000,
0x3f353f35,0x3f35bf35,0xbf35bf35,0xbf353f35,0x3f800000,0xbf80,0xbf800000,0x3f80,0x3f35bf35,0xbf35bf35,0xbf353f35,0x3f353f35,
0x80003f80,0x3f800000,0x80003f80,0x3f800000,0x3f800000,0xbf80,0x3f800000,0xbf80,0x8000bf80,0xbf800000,0x8000bf80,0xbf800000,
0xbf800000,0x3f80,0xbf800000,0x3f80,0x80003f80,0x3f800000,0x8000bf80,0xbf800000,0x3f35bf35,0xbf35bf35,0xbf353f35,0x3f353f35,
0xbf800000,0x3f80,0x3f800000,0xbf80,0x3f353f35,0x3f35bf35,0xbf35bf35,0xbf353f35,0x80003f80,0x3f800000,0x80003f80,0x3f800000,
0x8000bf80,0xbf800000,0x8000bf80,0xbf800000,0x80003f80,0x3f800000,0x80003f80,0x3f800000,0x8000bf80,0xbf800000,0x8000bf80,0xbf800000,
0x80003f80,0x3f800000,0x8000bf80,0xbf800000,0xbf35bf35,0xbf353f35,0x3f353f35,0x3f35bf35,0x3f800000,0xbf80,0xbf800000,0x3f80,
0xbf353f35,0x3f353f35,0x3f35bf35,0xbf35bf35,0x80003f80,0x3f800000,0x80003f80,0x3f800000,0xbf800000,0x3f80,0xbf800000,0x3f80,
0x8000bf80,0xbf800000,0x8000bf80,0xbf800000,0x3f800000,0xbf80,0x3f800000,0xbf80,0x80003f80,0x3f800000,0x8000bf80,0xbf800000,
0xbf353f35,0x3f353f35,0x3f35bf35,0xbf35bf35,0xbf800000,0x3f80,0x3f800000,0xbf80,0xbf35bf35,0xbf353f35,0x3f353f35,0x3f35bf35,
0x3f803f80,0x80008000,0x80008000,0xbf80bf80,0x3f803f80,0x80008000,0x80008000,0xbf80bf80,0x3f803f80,0x80008000,0x80008000,0xbf80bf80,
0x3f803f80,0x80008000,0x80008000,0xbf80bf80,0x3f353f80,0x3f358000,0x3f358000,0xbf35bf80,0xbf350000,0x3f353f80,0x3f353f80,0x3f358000,
0xbf35bf80,0xbf358000,0xbf358000,0x3f353f80,0x3f350000,0xbf35bf80,0xbf35bf80,0xbf358000,0x3f80,0x3f808000,0x3f808000,0x8000bf80,
0xbf80,0xbf808000,0xbf808000,0x80003f80,0x3f80,0x3f808000,0x3f808000,0x8000bf80,0xbf80,0xbf808000,0xbf808000,0x80003f80,
0xbf353f80,0x3f358000,0x3f358000,0x3f35bf80,0x3f350000,0x3f35bf80,0x3f35bf80,0xbf358000,0x3f35bf80,0xbf358000,0xbf358000,0xbf353f80,
0xbf350000,0xbf353f80,0xbf353f80,0x3f358000,0xbf803f80,0x80008000,0x80008000,0x3f80bf80,0xbf803f80,0x80008000,0x80008000,0x3f80bf80,
0xbf803f80,0x80008000,0x80008000,0x3f80bf80,0xbf803f80,0x80008000,0x80008000,0x3f80bf80,0xbf353f80,0xbf358000,0xbf358000,0x3f35bf80,
0x3f350000,0xbf353f80,0xbf353f80,0xbf358000,0x3f35bf80,0x3f358000,0x3f358000,0xbf353f80,0xbf350000,0x3f35bf80,0x3f35bf80,0x3f358000,
0x3f80,0xbf808000,0xbf808000,0x8000bf80,0xbf80,0x3f808000,0x3f808000,0x80003f80,0x3f80,0xbf808000,0xbf808000,0x8000bf80,
0xbf80,0x3f808000,0x3f808000,0x80003f80,0x3f353f80,0xbf358000,0xbf358000,0xbf35bf80,0xbf350000,0xbf35bf80,0xbf35bf80,0x3f358000,
0xbf35bf80,0x3f358000,0x3f358000,0x3f353f80,0x3f350000,0x3f353f80,0x3f353f80,0xbf358000,0x3f800000,0x0,0x3f800000,0x0,
0x3f800000,0x0,0x3f800000,0x0,0x3f800000,0x0,0x3f800000,0x0,0x3f800000,0x0,0x3f800000,0x0,
0x3f800000,0x0,0x3f7fb10f,0xbd48fb30,0x3f7ec46d,0xbdc8bd36,0x3f7d3aac,0xbe164083,0x3f7b14be,0xbe47c5c2,0x3f7853f8,0xbe78cfcc,
0x3f74fa0b,0xbe94a031,0x3f710908,0xbeac7cd4,0x3f800000,0x0,0x3f7ec46d,0xbdc8bd36,0x3f7b14be,0xbe47c5c2,0x3f74fa0b,0xbe94a031,
0x3f6c835e,0xbec3ef15,0x3f61c598,0xbef15aea,0x3f54db31,0xbf0e39da,0x3f45e403,0xbf226799,0x3f800000,0x0,0x3f7d3aac,0xbe164083,
0x3f74fa0b,0xbe94a031,0x3f676bd8,0xbedae880,0x3f54db31,0xbf0e39da,0x3f3daef9,0xbf2beb4a,0x3f226799,0xbf45e403,0x3f039c3d,0xbf5b941a,
0x3f800000,0x0,0x3f7b14be,0xbe47c5c2,0x3f6c835e,0xbec3ef15,0x3f54db31,0xbf0e39da,0x3f3504f3,0xbf3504f3,0x3f0e39da,0xbf54db31,
0x3ec3ef15,0xbf6c835e,0x3e47c5c2,0xbf7b14be,0x3f800000,0x0,0x3f7853f8,0xbe78cfcc,0x3f61c598,0xbef15aea,0x3f3daef9,0xbf2beb4a,
0x3f0e39da,0xbf54db31,0x3eac7cd4,0xbf710908,0x3dc8bd36,0xbf7ec46d,0xbe164083,0xbf7d3aac,0x3f800000,0x0,0x3f74fa0b,0xbe94a031,
0x3f54db31,0xbf0e39da,0x3f226799,0xbf45e403,0x3ec3ef15,0xbf6c835e,0x3dc8bd36,0xbf7ec46d,0xbe47c5c2,0xbf7b14be,0xbef15aea,0xbf61c598,
0x3f800000,0x0,0x3f710908,0xbeac7cd4,0x3f45e403,0xbf226799,0x3f039c3d,0xbf5b941a,0x3e47c5c2,0xbf7b14be,0xbe164083,0xbf7d3aac,
0xbef15aea,0xbf61c598,0xbf3daef9,0xbf2beb4a,0x3f800000,0x0,0x3f800000,0x0,0x3f800000,0x0,0x3f800000,0x0,
0x3f800000,0x0,0x3f800000,0x0,0x3f800000,0x0,0x3f800000,0x0,0x3f6c835e,0xbec3ef15,0x3f676bd8,0xbedae880,
0x3f61c598,0xbef15aea,0x3f5b941a,0xbf039c3d,0x3f54db31,0xbf0e39da,0x3f4d9f02,0xbf187fc0,0x3f45e403,0xbf226799,0x3f3daef9,0xbf2beb4a,
0x3f3504f3,0xbf3504f3,0x3f226799,0xbf45e403,0x3f0e39da,0xbf54db31,0x3ef15aea,0xbf61c598,0x3ec3ef15,0xbf6c835e,0x3e94a031,0xbf74fa0b,
0x3e47c5c2,0xbf7b14be,0x3dc8bd36,0xbf7ec46d,0x3ec3ef15,0xbf6c835e,0x3e78cfcc,0xbf7853f8,0x3dc8bd36,0xbf7ec46d,0xbd48fb30,0xbf7fb10f,
0xbe47c5c2,0xbf7b14be,0xbeac7cd4,0xbf710908,0xbef15aea,0xbf61c598,0xbf187fc0,0xbf4d9f02,0x0,0xbf800000,0xbe47c5c2,0xbf7b14be,
0xbec3ef15,0xbf6c835e,0xbf0e39da,0xbf54db31,0xbf3504f3,0xbf3504f3,0xbf54db31,0xbf0e39da,0xbf6c835e,0xbec3ef15,0xbf7b14be,0xbe47c5c2,
0xbec3ef15,0xbf6c835e,0xbf187fc0,0xbf4d9f02,0xbf45e403,0xbf226799,0xbf676bd8,0xbedae880,0xbf7b14be,0xbe47c5c2,0xbf7fb10f,0x3d48fb30,
0xbf74fa0b,0x3e94a031,0xbf5b941a,0x3f039c3d,0xbf3504f3,0xbf3504f3,0xbf61c598,0xbef15aea,0xbf7b14be,0xbe47c5c2,0xbf7ec46d,0x3dc8bd36,
0xbf6c835e,0x3ec3ef15,0xbf45e403,0x3f226799,0xbf0e39da,0x3f54db31,0xbe94a031,0x3f74fa0b,0xbf6c835e,0xbec3ef15,0xbf7fb10f,0xbd48fb30,
0xbf74fa0b,0x3e94a031,0xbf4d9f02,0x3f187fc0,0xbf0e39da,0x3f54db31,0xbe78cfcc,0x3f7853f8,0x3dc8bd36,0x3f7ec46d,0x3edae880,0x3f676bd8,
0x80003f80,0x3f800000,0x3f800000,0xbf80,0x3ec43f6d,0x3f6dbec4,0x3f6dbec4,0xbec4bf6d,0x3f353f35,0x3f35bf35,0x3f35bf35,0xbf35bf35,
0x3f6d3ec4,0x3ec4bf6d,0x3ec4bf6d,0xbf6dbec4,0x80003f80,0x3f800000,0xbf800000,0x3f80,0x3f6d3ec4,0x3ec4bf6d,0xbec43f6d,0x3f6d3ec4,
0x3f35bf35,0xbf35bf35,0x3f353f35,0x3f35bf35,0xbec4bf6d,0xbf6d3ec4,0x3f6dbec4,0xbec4bf6d,0x80003f80,0x3f800000,0x3f800000,0xbf80,
0x3f6dbec4,0xbec4bf6d,0xbec4bf6d,0xbf6d3ec4,0xbf35bf35,0xbf353f35,0xbf353f35,0x3f353f35,0xbec43f6d,0x3f6d3ec4,0x3f6d3ec4,0x3ec4bf6d,
0x80003f80,0x3f800000,0xbf800000,0x3f80,0x3ec4bf6d,0xbf6dbec4,0x3f6d3ec4,0x3ec4bf6d,0xbf353f35,0x3f353f35,0xbf35bf35,0xbf353f35,
0x3f6dbec4,0xbec4bf6d,0x3ec43f6d,0x3f6dbec4,0x80003f80,0x3f800000,0x3f800000,0xbf80,0xbec4bf6d,0xbf6d3ec4,0xbf6d3ec4,0x3ec43f6d,
0x3f353f35,0x3f35bf35,0x3f35bf35,0xbf35bf35,0xbf6dbec4,0xbec43f6d,0xbec43f6d,0x3f6d3ec4,0x80003f80,0x3f800000,0xbf800000,0x3f80,
0xbf6dbec4,0xbec43f6d,0x3ec4bf6d,0xbf6dbec4,0x3f35bf35,0xbf35bf35,0x3f353f35,0x3f35bf35,0x3ec43f6d,0x3f6dbec4,0xbf6d3ec4,0x3ec43f6d,
0x80003f80,0x3f800000,0x3f800000,0xbf80,0xbf6d3ec4,0x3ec43f6d,0x3ec43f6d,0x3f6dbec4,0xbf35bf35,0xbf353f35,0xbf353f35,0x3f353f35,
0x3ec4bf6d,0xbf6dbec4,0xbf6dbec4,0xbec43f6d,0x80003f80,0x3f800000,0xbf800000,0x3f80,0xbec43f6d,0x3f6d3ec4,0xbf6dbec4,0xbec43f6d,
0xbf353f35,0x3f353f35,0xbf35bf35,0xbf353f35,0xbf6d3ec4,0x3ec43f6d,0xbec4bf6d,0xbf6d3ec4,0x3f803f80,0x80008000,0x80008000,0xbf80bf80,
0x3f803f80,0x80008000,0x80008000,0xbf80bf80,0x3f803f80,0x80008000,0x80008000,0xbf80bf80,0x3f803f80,0x80008000,0x80008000,0xbf80bf80,
0x3ec43f6d,0x3f6d3ec4,0x3f6d3ec4,0xbec4bf6d,0xbf6dbec4,0x3ec43f6d,0x3ec43f6d,0x3f6d3ec4,0xbec4bf6d,0xbf6dbec4,0xbf6dbec4,0x3ec43f6d,
0x3f6d3ec4,0xbec4bf6d,0xbec4bf6d,0xbf6dbec4,0xbf353f35,0x3f353f35,0x3f353f35,0x3f35bf35,0x3f35bf35,0xbf35bf35,0xbf35bf35,0xbf353f35,
0xbf353f35,0x3f353f35,0x3f353f35,0x3f35bf35,0x3f35bf35,0xbf35bf35,0xbf35bf35,0xbf353f35,0xbf6d3ec4,0xbec43f6d,0xbec43f6d,0x3f6dbec4,
0xbec43f6d,0x3f6dbec4,0x3f6dbec4,0x3ec4bf6d,0x3f6dbec4,0x3ec4bf6d,0x3ec4bf6d,0xbf6d3ec4,0x3ec4bf6d,0xbf6d3ec4,0xbf6d3ec4,0xbec43f6d,
0x0,0xbf803f80,0xbf803f80,0x80008000,0x0,0xbf803f80,0xbf803f80,0x80008000,0x0,0xbf803f80,0xbf803f80,0x80008000,
0x0,0xbf803f80,0xbf803f80,0x80008000,0x3f6dbec4,0xbec43f6d,0xbec43f6d,0xbf6d3ec4,0x3ec4bf6d,0x3f6dbec4,0x3f6dbec4,0xbec43f6d,
0xbf6d3ec4,0x3ec4bf6d,0x3ec4bf6d,0x3f6dbec4,0xbec43f6d,0xbf6d3ec4,0xbf6d3ec4,0x3ec4bf6d,0x3f35bf35,0x3f353f35,0x3f353f35,0xbf353f35,
0xbf353f35,0xbf35bf35,0xbf35bf35,0x3f35bf35,0x3f35bf35,0x3f353f35,0x3f353f35,0xbf353f35,0xbf353f35,0xbf35bf35,0xbf35bf35,0x3f35bf35,
0xbec4bf6d,0x3f6d3ec4,0x3f6d3ec4,0x3ec43f6d,0x3f6d3ec4,0x3ec43f6d,0x3ec43f6d,0xbf6dbec4,0x3ec43f6d,0xbf6dbec4,0xbf6dbec4,0xbec4bf6d,
0xbf6dbec4,0xbec4bf6d,0xbec4bf6d,0x3f6d3ec4,0x3f800000,0x0,0x3f7fec43,0xbcc90ab0,0x3f7fb10f,0xbd48fb30,0x3f7f4e6d,0xbd96a905,
0x3f7ec46d,0xbdc8bd36,0x3f7e1324,0xbdfab273,0x3f7d3aac,0xbe164083,0x3f7c3b28,0xbe2f10a2,0x3f800000,0x0,0x3f7f4e6d,0xbd96a905,
0x3f7d3aac,0xbe164083,0x3f79c79d,0xbe605c13,0x3f74fa0b,0xbe94a031,0x3f6ed89e,0xbeb8442a,0x3f676bd8,0xbedae880,0x3f5ebe05,0xbefc5d27,
0x3f800000,0x0,0x3f7e1324,0xbdfab273,0x3f7853f8,0xbe78cfcc,0x3f6ed89e,0xbeb8442a,0x3f61c598,0xbef15aea,0x3f514d3d,0xbf13682a,
0x3f3daef9,0xbf2beb4a,0x3f273656,0xbf41d870,0x3f800000,0x0,0x3f7c3b28,0xbe2f10a2,0x3f710908,0xbeac7cd4,0x3f5ebe05,0xbefc5d27,
0x3f45e403,0xbf226799,0x3f273656,0xbf41d870,0x3f039c3d,0xbf5b941a,0x3eb8442a,0xbf6ed89e,0x3f800000,0x0,0x3f79c79d,0xbe605c13,
0x3f676bd8,0xbedae880,0x3f49d112,0xbf1d7fd1,0x3f226799,0xbf45e403,0x3ee63375,0xbf64aa59,0x3e78cfcc,0xbf7853f8,0x3cc90ab0,0xbf7fec43,
0x3f800000,0x0,0x3f76ba07,0xbe888e93,0x3f5b941a,0xbf039c3d,0x3f3085bb,0xbf396842,0x3ef15aea,0xbf61c598,0x3e605c13,0xbf79c79d,
0xbd48fb30,0xbf7fb10f,0xbea09ae5,0xbf731447,0x3f800000,0x0,0x3f731447,0xbea09ae5,0x3f4d9f02,0xbf187fc0,0x3f13682a,0xbf514d3d,
0x3e94a031,0xbf74fa0b,0xbcc90ab0,0xbf7fec43,0xbeac7cd4,0xbf710908,0xbf1d7fd1,0xbf49d112,0x3f800000,0x0,0x3f6ed89e,0xbeb8442a,
0x3f3daef9,0xbf2beb4a,0x3ee63375,0xbf64aa59,0x3dc8bd36,0xbf7ec46d,0xbe888e93,0xbf76ba07,0xbf187fc0,0xbf4d9f02,0xbf584853,0xbf08f59b,
0x3f7b14be,0xbe47c5c2,0x3f79c79d,0xbe605c13,0x3f7853f8,0xbe78cfcc,0x3f76ba07,0xbe888e93,0x3f74fa0b,0xbe94a031,0x3f731447,0xbea09ae5,
0x3f710908,0xbeac7cd4,0x3f6ed89e,0xbeb8442a,0x3f54db31,0xbf0e39da,0x3f49d112,0xbf1d7fd1,0x3f3daef9,0xbf2beb4a,0x3f3085bb,0xbf396842,
0x3f226799,0xbf45e403,0x3f13682a,0xbf514d3d,0x3f039c3d,0xbf5b941a,0x3ee63375,0xbf64aa59,0x3f0e39da,0xbf54db31,0x3ee63375,0xbf64aa59,
0x3eac7cd4,0xbf710908,0x3e605c13,0xbf79c79d,0x3dc8bd36,0xbf7ec46d,0xbcc90ab0,0xbf7fec43,0xbe164083,0xbf7d3aac,0xbe888e93,0xbf76ba07,
0x3e47c5c2,0xbf7b14be,0x3cc90ab0,0xbf7fec43,0xbe164083,0xbf7d3aac,0xbea09ae5,0xbf731447,0xbef15aea,0xbf61c598,0xbf1d7fd1,0xbf49d112,
0xbf3daef9,0xbf2beb4a,0xbf584853,0xbf08f59b,0xbe47c5c2,0xbf7b14be,0xbecf7bca,0xbf6a09a7,0xbf187fc0,0xbf4d9f02,0xbf41d870,0xbf273656,
0xbf61c598,0xbef15aea,0xbf76ba07,0xbe888e93,0xbf7fb10f,0xbd48fb30,0xbf7c3b28,0x3e2f10a2,0xbf0e39da,0xbf54db31,0xbf41d870,0xbf273656,
0xbf676bd8,0xbedae880,0xbf7c3b28,0xbe2f10a2,0xbf7ec46d,0x3dc8bd36,0xbf6ed89e,0x3eb8442a,0xbf4d9f02,0x3f187fc0,0xbf1d7fd1,0x3f49d112,
0xbf54db31,0xbf0e39da,0xbf76ba07,0xbe888e93,0xbf7fb10f,0x3d48fb30,0xbf6ed89e,0x3eb8442a,0xbf45e403,0x3f226799,0xbf08f59b,0x3f584853,
0xbe78cfcc,0x3f7853f8,0x3d96a905,0x3f7f4e6d,0xbf7b14be,0xbe47c5c2,0xbf7c3b28,0x3e2f10a2,0xbf5b941a,0x3f039c3d,0xbf1d7fd1,0x3f49d112,
0xbe94a031,0x3f74fa0b,0x3d96a905,0x3f7f4e6d,0x3edae880,0x3f676bd8,0x3f396842,0x3f3085bb,0x80003f80,0x80003f80,0x80003f80,0x80003f80,
0x80003f80,0x80003f80,0x80003f80,0x80003f80,0x80003f80,0x80003f80,0x80003f80,0x80003f80,0x80003f80,0x80003f80,0x80003f80,0x80003f80,
0x3f800000,0x3f800000,0x3f800000,0x3f800000,0x3f800000,0x3f800000,0x3f800000,0x3f800000,0x3f800000,0x3f800000,0x3f800000,0x3f800000,
0x3f800000,0x3f800000,0x3f800000,0x3f800000,0x80003f80,0x3f353f35,0x80003f80,0x3f353f35,0x3f800000,0x3f35bf35,0x3f800000,0x3f35bf35,
0x8000bf80,0xbf35bf35,0x8000bf80,0xbf35bf35,0xbf800000,0xbf353f35,0xbf800000,0xbf353f35,0x3f800000,0x3f35bf35,0x3f800000,0x3f35bf35,
0xbf80,0xbf35bf35,0xbf80,0xbf35bf35,0xbf800000,0xbf353f35,0xbf800000,0xbf353f35,0x3f80,0x3f353f35,0x3f80,0x3f353f35,
0x80003f80,0x3f800000,0x80003f80,0x3f800000,0x8000bf80,0xbf800000,0x8000bf80,0xbf800000,0x80003f80,0x3f800000,0x80003f80,0x3f800000,
0x8000bf80,0xbf800000,0x8000bf80,0xbf800000,0x3f800000,0xbf80,0x3f800000,0xbf80,0xbf800000,0x3f80,0xbf800000,0x3f80,
0x3f800000,0xbf80,0x3f800000,0xbf80,0xbf800000,0x3f80,0xbf800000,0x3f80,0x80003f80,0x3f35bf35,0x80003f80,0x3f35bf35,
0xbf800000,0x3f353f35,0xbf800000,0x3f353f35,0x8000bf80,0xbf353f35,0x8000bf80,0xbf353f35,0x3f800000,0xbf35bf35,0x3f800000,0xbf35bf35,
0x3f800000,0xbf35bf35,0x3f800000,0xbf35bf35,0x3f80,0x3f35bf35,0x3f80,0x3f35bf35,0xbf800000,0x3f353f35,0xbf800000,0x3f353f35,
0xbf80,0xbf353f35,0xbf80,0xbf353f35,0x80003f80,0x3ec43f6d,0x8000bf80,0xbec4bf6d,0x3f353f35,0x3f6d3ec4,0xbf35bf35,0xbf6dbec4,
0x3f800000,0x3f6dbec4,0xbf800000,0xbf6d3ec4,0x3f35bf35,0x3ec4bf6d,0xbf353f35,0xbec43f6d,0x3f800000,0x3f6dbec4,0xbf800000,0xbf6d3ec4,
0x3f35bf35,0x3ec4bf6d,0xbf353f35,0xbec43f6d,0xbf80,0xbec4bf6d,0x3f80,0x3ec43f6d,0xbf35bf35,0xbf6dbec4,0x3f353f35,0x3f6d3ec4,
0x80003f80,0x3f6d3ec4,0x8000bf80,0xbf6dbec4,0x3f35bf35,0xbec4bf6d,0xbf353f35,0x3ec43f6d,0xbf800000,0xbec43f6d,0x3f800000,0x3ec4bf6d,
0x3f353f35,0x3f6dbec4,0xbf35bf35,0xbf6d3ec4,0x3f800000,0x3ec4bf6d,0xbf800000,0xbec43f6d,0xbf35bf35,0xbf6d3ec4,0x3f353f35,0x3f6dbec4,
0x3f80,0x3f6d3ec4,0xbf80,0xbf6dbec4,0x3f35bf35,0xbec4bf6d,0xbf353f35,0x3ec43f6d,0x80003f80,0x3f6dbec4,0x8000bf80,0xbf6d3ec4,
0xbf35bf35,0xbec43f6d,0x3f353f35,0x3ec4bf6d,0x3f800000,0xbec4bf6d,0xbf800000,0x3ec43f6d,0xbf353f35,0x3f6d3ec4,0x3f35bf35,0xbf6dbec4,
0x3f800000,0xbec4bf6d,0xbf800000,0x3ec43f6d,0xbf353f35,0x3f6d3ec4,0x3f35bf35,0xbf6dbec4,0xbf80,0xbf6d3ec4,0x3f80,0x3f6dbec4,
0x3f353f35,0x3ec4bf6d,0xbf35bf35,0xbec43f6d,0x80003f80,0x3ec4bf6d,0x8000bf80,0xbec43f6d,0xbf353f35,0x3f6dbec4,0x3f35bf35,0xbf6d3ec4,
0xbf800000,0x3f6d3ec4,0x3f800000,0xbf6dbec4,0xbf35bf35,0x3ec43f6d,0x3f353f35,0xbec4bf6d,0x3f800000,0xbf6dbec4,0xbf800000,0x3f6d3ec4,
0x3f353f35,0xbec4bf6d,0xbf35bf35,0x3ec43f6d,0x3f80,0x3ec4bf6d,0xbf80,0xbec43f6d,0xbf353f35,0x3f6dbec4,0x3f35bf35,0xbf6d3ec4,
0x80003f80,0x8000bf80,0x80003f80,0x8000bf80,0x80003f80,0x8000bf80,0x80003f80,0x8000bf80,0x80003f80,0x8000bf80,0x80003f80,0x8000bf80,
0x80003f80,0x8000bf80,0x80003f80,0x8000bf80,0x3f800000,0xbf800000,0x3f800000,0xbf800000,0x3f800000,0xbf800000,0x3f800000,0xbf800000,
0x3f800000,0xbf800000,0x3f800000,0xbf800000,0x3f800000,0xbf800000,0x3f800000,0xbf800000,0x80003f80,0xbf35bf35,0x80003f80,0xbf35bf35,
0x3f800000,0xbf353f35,0x3f800000,0xbf353f35,0x8000bf80,0x3f353f35,0x8000bf80,0x3f353f35,0xbf800000,0x3f35bf35,0xbf800000,0x3f35bf35,
0x3f800000,0xbf353f35,0x3f800000,0xbf353f35,0xbf80,0x3f353f35,0xbf80,0x3f353f35,0xbf800000,0x3f35bf35,0xbf800000,0x3f35bf35,
0x3f80,0xbf35bf35,0x3f80,0xbf35bf35,0x80003f80,0xbf800000,0x80003f80,0xbf800000,0x8000bf80,0x3f800000,0x8000bf80,0x3f800000,
0x80003f80,0xbf800000,0x80003f80,0xbf800000,0x8000bf80,0x3f800000,0x8000bf80,0x3f800000,0x3f800000,0x3f80,0x3f800000,0x3f80,
0xbf800000,0xbf80,0xbf800000,0xbf80,0x3f800000,0x3f80,0x3f800000,0x3f80,0xbf800000,0xbf80,0xbf800000,0xbf80,
0x80003f80,0xbf353f35,0x80003f80,0xbf353f35,0xbf800000,0xbf35bf35,0xbf800000,0xbf35bf35,0x8000bf80,0x3f35bf35,0x8000bf80,0x3f35bf35,
0x3f800000,0x3f353f35,0x3f800000,0x3f353f35,0x3f800000,0x3f353f35,0x3f800000,0x3f353f35,0x3f80,0xbf353f35,0x3f80,0xbf353f35,
0xbf800000,0xbf35bf35,0xbf800000,0xbf35bf35,0xbf80,0x3f35bf35,0xbf80,0x3f35bf35,0x80003f80,0xbec4bf6d,0x8000bf80,0x3ec43f6d,
0x3f353f35,0xbf6dbec4,0xbf35bf35,0x3f6d3ec4,0x3f800000,0xbf6d3ec4,0xbf800000,0x3f6dbec4,0x3f35bf35,0xbec43f6d,0xbf353f35,0x3ec4bf6d,
0x3f800000,0xbf6d3ec4,0xbf800000,0x3f6dbec4,0x3f35bf35,0xbec43f6d,0xbf353f35,0x3ec4bf6d,0xbf80,0x3ec43f6d,0x3f80,0xbec4bf6d,
0xbf35bf35,0x3f6d3ec4,0x3f353f35,0xbf6dbec4,0x80003f80,0xbf6dbec4,0x8000bf80,0x3f6d3ec4,0x3f35bf35,0x3ec43f6d,0xbf353f35,0xbec4bf6d,
0xbf800000,0x3ec4bf6d,0x3f800000,0xbec43f6d,0x3f353f35,0xbf6d3ec4,0xbf35bf35,0x3f6dbec4,0x3f800000,0xbec43f6d,0xbf800000,0x3ec4bf6d,
0xbf35bf35,0x3f6dbec4,0x3f353f35,0xbf6d3ec4,0x3f80,0xbf6dbec4,0xbf80,0x3f6d3ec4,0x3f35bf35,0x3ec43f6d,0xbf353f35,0xbec4bf6d,
0x80003f80,0xbf6d3ec4,0x8000bf80,0x3f6dbec4,0xbf35bf35,0x3ec4bf6d,0x3f353f35,0xbec43f6d,0x3f800000,0x3ec43f6d,0xbf800000,0xbec4bf6d,
0xbf353f35,0xbf6dbec4,0x3f35bf35,0x3f6d3ec4,0x3f800000,0x3ec43f6d,0xbf800000,0xbec4bf6d,0xbf353f35,0xbf6dbec4,0x3f35bf35,0x3f6d3ec4,
0xbf80,0x3f6dbec4,0x3f80,0xbf6d3ec4,0x3f353f35,0xbec43f6d,0xbf35bf35,0x3ec4bf6d,0x80003f80,0xbec43f6d,0x8000bf80,0x3ec4bf6d,
0xbf353f35,0xbf6d3ec4,0x3f35bf35,0x3f6dbec4,0xbf800000,0xbf6dbec4,0x3f800000,0x3f6d3ec4,0xbf35bf35,0xbec4bf6d,0x3f353f35,0x3ec43f6d,
0x3f800000,0x3f6d3ec4,0xbf800000,0xbf6dbec4,0x3f353f35,0x3ec43f6d,0xbf35bf35,0xbec4bf6d,0x3f80,0xbec43f6d,0xbf80,0x3ec4bf6d,
0xbf353f35,0xbf6d3ec4,0x3f35bf35,0x3f6dbec4,
};
constexpr int TB_F = 0, TB_E = 512, TB_P2 = 1024;

enum { C_EP = 0, C_Z1 = 32, C_Z2 = 96, C_H3 = 128, C_U = 160, C_X = 256, C_TOTAL = 512 };
struct Scratch {
  unsigned cnt[C_TOTAL];
  uint32_t moda[8 * 2 * D_];
  uint32_t mod[4 * D_ + 256];
  uint32_t z1[120 * 5120];
  uint32_t z2[128 * 4800];
  uint8_t h3[32 * 18 * 4096];
  uint8_t u[72 * D_ * 128];
};
__device__ __align__(1024) Scratch g_s;

#define PF2 8
#define PF2K 16
#define HOLDA 5
#define GOAT 0
#define HW bulk_commit_wait
#define H3W 0
#define X1K 10
#define PEEK 1
#define H3G 1
#define PFF 2
#ifndef NV1
#define NV1 12
#endif
#ifndef NV2
#define NV2 20
#endif
#define GDEP 0
#define TRK0 50
#define W0N 3
#define TRKC 350
#define OSPL 2
#define NG1 2

#define FAILCNT(k) do {} while (0)
#define CK(k) do {} while (0)
#define CKX(k) do {} while (0)
#define TS(k) do {} while (0)
#define TSC(k) do {} while (0)
struct Maps { CUtensorMap z1, z2[2], w1a, w1b, h3[2], w2, out, wf[4], wm; };
struct Params {
  const __nv_bfloat16 *x, *c, *wmod;
  Scratch* s;
  const uint4* tab;
  const __nv_bfloat16 *wr, *wi, *w1, *w2, *b1, *b2;
  uint32_t* out;
};

__device__ __forceinline__ uint32_t smem_u32(const void* p) { return (uint32_t)__cvta_generic_to_shared(p); }
__device__ __forceinline__ void mbar_init(uint32_t b, int c) { asm volatile("mbarrier.init.shared::cta.b64 [%0], %1;" ::"r"(b), "r"(c)); }
__device__ __forceinline__ void mbar_expect(uint32_t b, int bytes) { asm volatile("mbarrier.arrive.expect_tx.shared::cta.b64 _, [%0], %1;" ::"r"(b), "r"(bytes) : "memory"); }
__device__ __forceinline__ void mbar_arrive(uint32_t b) { asm volatile("mbarrier.arrive.shared::cta.b64 _, [%0];" ::"r"(b) : "memory"); }
#define MBAR_WAIT(SEM)                                                                                                         \
  asm volatile("{\n.reg .pred p;\n.reg .u32 it;\nmov.u32 it, 0;\nW:\nmbarrier.try_wait.parity" SEM ".shared::cta.b64 p, [%0], %1;\n" \
               "@p bra.uni D;\nadd.u32 it, it, 1;\nsetp.lt.u32 p, it, 0x400000;\n@p bra.uni W;\ntrap;\nD:\n}" ::"r"(b), "r"(ph) : "memory")
__device__ __forceinline__ void mbar_wait(uint32_t b, int ph) { MBAR_WAIT(""); }
__device__ __forceinline__ uint32_t mbar_test(uint32_t b, int ph) {
  uint32_t ok;
  asm volatile("{\n.reg .pred p;\nmbarrier.test_wait.parity.shared::cta.b64 p, [%1], %2;\nselp.u32 %0, 1, 0, p;\n}\n" : "=r"(ok) : "r"(b), "r"(ph) : "memory");
  return ok;
}
__device__ __forceinline__ void tma2d(uint32_t dst, const CUtensorMap* m, int c0, int c1, uint32_t bar) {
  asm volatile("cp.async.bulk.tensor.2d.shared::cluster.global.mbarrier::complete_tx::bytes [%0], [%1, {%3, %4}], [%2];" ::"r"(dst), "l"(m), "r"(bar), "r"(c0), "r"(c1) : "memory");
}
__device__ __forceinline__ uint64_t pol_ef() { uint64_t p; asm("createpolicy.fractional.L2::evict_first.b64 %0, 1.0;" : "=l"(p)); return p; }
__device__ __forceinline__ void tma3d_ef(uint32_t dst, const CUtensorMap* m, int c1, int c2, uint32_t bar) {
  asm volatile("cp.async.bulk.tensor.3d.shared::cluster.global.mbarrier::complete_tx::bytes.L2::cache_hint [%0], [%1, {%3, %4, %5}], [%2], %6;" ::"r"(dst), "l"(m), "r"(bar), "r"(0), "r"(c1), "r"(c2), "l"(pol_ef()) : "memory");
}
__device__ __forceinline__ void tma4d_ef(uint32_t dst, const CUtensorMap* m, int c1, int c2, int c3, uint32_t bar) {
  asm volatile("cp.async.bulk.tensor.4d.shared::cluster.global.mbarrier::complete_tx::bytes.L2::cache_hint [%0], [%1, {%3, %7, %4, %5}], [%2], %6;" ::"r"(dst), "l"(m), "r"(bar), "r"(0), "r"(c2), "r"(c3), "l"(pol_ef()), "r"(c1) : "memory");
}
__device__ __forceinline__ void bulk_ld(uint32_t dst, const void* src, int bytes, uint32_t bar) {
  asm volatile("cp.async.bulk.shared::cluster.global.mbarrier::complete_tx::bytes [%0], [%1], %2, [%3];" ::"r"(dst), "l"(src), "r"(bytes), "r"(bar) : "memory");
}
__device__ __forceinline__ void bulk_st(void* dst, uint32_t src, int bytes) {
  asm volatile("cp.async.bulk.global.shared::cta.bulk_group [%0], [%1], %2;" ::"l"(dst), "r"(src), "r"(bytes) : "memory");
}
__device__ __forceinline__ void tma_st2d(const CUtensorMap* m, uint32_t src, int c0, int c1) {
  asm volatile("cp.async.bulk.tensor.2d.global.shared::cta.bulk_group [%0, {%2, %3}], [%1];" ::"l"(m), "r"(src), "r"(c0), "r"(c1) : "memory");
}
__device__ __forceinline__ void tma_st3d(const CUtensorMap* m, uint32_t src, int c0, int c1, int c2) {
  asm volatile("cp.async.bulk.tensor.3d.global.shared::cta.bulk_group [%0, {%2, %3, %4}], [%1];" ::"l"(m), "r"(src), "r"(c0), "r"(c1), "r"(c2) : "memory");
}
__device__ __forceinline__ void bulk_commit_wait_read() {
  asm volatile("cp.async.bulk.commit_group;" ::: "memory");
  asm volatile("cp.async.bulk.wait_group.read 0;" ::: "memory");
}
__device__ __forceinline__ void bulk_commit_wait() {
  asm volatile("cp.async.bulk.commit_group;" ::: "memory");
  asm volatile("cp.async.bulk.wait_group 0;" ::: "memory");
}
__device__ __forceinline__ void prefetch_l2(const void* p, int bytes) {
  asm volatile("cp.async.bulk.prefetch.L2.global [%0], %1;" ::"l"(p), "r"(bytes) : "memory");
}
__device__ __forceinline__ void wg_fence() { asm volatile("wgmma.fence.sync.aligned;" ::: "memory"); }
__device__ __forceinline__ void wg_commit() { asm volatile("wgmma.commit_group.sync.aligned;" ::: "memory"); }
template <int N> __device__ __forceinline__ void wg_wait() { asm volatile("wgmma.wait_group.sync.aligned %0;" ::"n"(N) : "memory"); }
template <int N> __device__ __forceinline__ void reg_fence(float (&d)[N]) {
#pragma unroll
  for (int i = 0; i < N; i++) asm volatile("" : "+f"(d[i])::"memory");
}
__device__ __forceinline__ void fence_async_smem() { asm volatile("fence.proxy.async.shared::cta;" ::: "memory"); }
__device__ __forceinline__ void fence_async_glb() { asm volatile("fence.proxy.async.global;" ::: "memory"); }
__device__ __forceinline__ uint32_t ld_rlx(const void* p) { uint32_t v; asm volatile("ld.relaxed.gpu.global.b32 %0, [%1];" : "=r"(v) : "l"(p) : "memory"); return v; }
__device__ __forceinline__ uint2 ld_rlx2(const void* p) { uint2 v; asm volatile("ld.relaxed.gpu.global.v2.b32 {%0,%1}, [%2];" : "=r"(v.x), "=r"(v.y) : "l"(p) : "memory"); return v; }
__device__ __forceinline__ uint4 ld_rlx4(const void* p) { uint4 v; asm volatile("ld.relaxed.gpu.global.v4.b32 {%0,%1,%2,%3}, [%4];" : "=r"(v.x), "=r"(v.y), "=r"(v.z), "=r"(v.w) : "l"(p) : "memory"); return v; }
__device__ __forceinline__ uint32_t ld_nc(const void* p) { uint32_t v; asm volatile("ld.global.nc.L1::no_allocate.b32 %0, [%1];" : "=r"(v) : "l"(p) : "memory"); return v; }
__device__ __forceinline__ uint4 ld_nc4(const void* p) { uint4 v; asm volatile("ld.global.nc.v4.b32 {%0,%1,%2,%3}, [%4];" : "=r"(v.x), "=r"(v.y), "=r"(v.z), "=r"(v.w) : "l"(p) : "memory"); return v; }
__device__ __forceinline__ uint32_t lds(uint32_t a) { uint32_t v; asm volatile("ld.shared.b32 %0, [%1];" : "=r"(v) : "r"(a) : "memory"); return v; }
__device__ __forceinline__ uint2 lds2(uint32_t a) { uint2 v; asm volatile("ld.shared.v2.b32 {%0,%1}, [%2];" : "=r"(v.x), "=r"(v.y) : "r"(a) : "memory"); return v; }
__device__ __forceinline__ uint4 lds4(uint32_t a) { uint4 v; asm volatile("ld.shared.v4.b32 {%0,%1,%2,%3}, [%4];" : "=r"(v.x), "=r"(v.y), "=r"(v.z), "=r"(v.w) : "r"(a) : "memory"); return v; }
__device__ __forceinline__ float lds_bf(uint32_t a) { uint32_t v; asm volatile("ld.shared.u16 %0, [%1];" : "=r"(v) : "r"(a) : "memory"); return __uint_as_float(v << 16); }
__device__ __forceinline__ void sts(uint32_t a, uint32_t v) { asm volatile("st.shared.b32 [%0], %1;" ::"r"(a), "r"(v) : "memory"); }
__device__ __forceinline__ void sts2(uint32_t a, uint32_t v0, uint32_t v1) { asm volatile("st.shared.v2.b32 [%0], {%1,%2};" ::"r"(a), "r"(v0), "r"(v1) : "memory"); }
__device__ __forceinline__ void sts4(uint32_t a, uint32_t v0, uint32_t v1, uint32_t v2, uint32_t v3) { asm volatile("st.shared.v4.b32 [%0], {%1,%2,%3,%4};" ::"r"(a), "r"(v0), "r"(v1), "r"(v2), "r"(v3) : "memory"); }
__device__ __forceinline__ void bar_sync(int id, int n) { asm volatile("bar.sync %0, %1;" ::"r"(id), "r"(n) : "memory"); }
__device__ __forceinline__ void bar_arrive(int id, int n) { asm volatile("bar.arrive %0, %1;" ::"r"(id), "r"(n) : "memory"); }
__device__ __forceinline__ void red_add(unsigned* p, unsigned v) { asm volatile("red.relaxed.gpu.global.add.u32 [%0], %1;" ::"l"(p), "r"(v) : "memory"); }
__device__ __forceinline__ bool any(bool p) { return __any_sync(0xffffffffu, p); }
__device__ __forceinline__ void pause(unsigned clks) {
  asm volatile("{\n.reg .pred p;\n.reg .u32 a, b;\nmov.u32 a, %%clock;\nW:\nmov.u32 b, %%clock;\nsub.u32 b, b, a;\nsetp.lt.s32 p, b, %0;\n@p bra.uni W;\n}" ::"r"(clks) : "memory");
}
constexpr int SPIN_MAX = 1 << 20;
__device__ __forceinline__ void wait_cnt(const unsigned* p, unsigned target) {
  int it = 0;
  while (any((int)(ld_rlx(p) - target) < 0) && ++it < SPIN_MAX) {}
}
__device__ __forceinline__ uint32_t pack_bf16(float lo, float hi) { uint32_t r; asm("cvt.rn.bf16x2.f32 %0, %1, %2;" : "=r"(r) : "f"(hi), "f"(lo)); return r; }
__device__ __forceinline__ float bf_lo(uint32_t v) { return __uint_as_float(v << 16); }
__device__ __forceinline__ float bf_hi(uint32_t v) { return __uint_as_float(v & 0xffff0000u); }
__device__ __forceinline__ uint32_t hadd2(uint32_t a, uint32_t b) { uint32_t r; asm("add.rn.bf16x2 %0, %1, %2;" : "=r"(r) : "r"(a), "r"(b)); return r; }
__device__ __forceinline__ uint32_t hmul2(uint32_t a, uint32_t b) { uint32_t r; asm("mul.rn.bf16x2 %0, %1, %2;" : "=r"(r) : "r"(a), "r"(b)); return r; }
__device__ __forceinline__ uint32_t hfma2(uint32_t a, uint32_t b, uint32_t c) { uint32_t r; asm("fma.rn.bf16x2 %0, %1, %2, %3;" : "=r"(r) : "r"(a), "r"(b), "r"(c)); return r; }
__device__ __forceinline__ float rbf(float x) { uint32_t r; asm("cvt.rn.bf16x2.f32 %0, %1, %2;" : "=r"(r) : "f"(x), "f"(0.0f)); return __uint_as_float(r); }
__device__ __forceinline__ void stmatrix4(uint32_t a, uint32_t r0, uint32_t r1, uint32_t r2, uint32_t r3) {
  asm volatile("stmatrix.sync.aligned.m8n8.x4.shared.b16 [%0], {%1,%2,%3,%4};" ::"r"(a), "r"(r0), "r"(r1), "r"(r2), "r"(r3) : "memory");
}
__device__ __forceinline__ void stmatrix2(uint32_t a, uint32_t r0, uint32_t r1) {
  asm volatile("stmatrix.sync.aligned.m8n8.x2.shared.b16 [%0], {%1,%2};" ::"r"(a), "r"(r0), "r"(r1) : "memory");
}
__device__ __forceinline__ void stmatrix4t(uint32_t a, uint32_t r0, uint32_t r1, uint32_t r2, uint32_t r3) {
  asm volatile("stmatrix.sync.aligned.m8n8.x4.trans.shared.b16 [%0], {%1,%2,%3,%4};" ::"r"(a), "r"(r0), "r"(r1), "r"(r2), "r"(r3) : "memory");
}
__device__ __forceinline__ uint32_t movm(uint32_t a) { uint32_t r; asm("movmatrix.sync.aligned.m8n8.trans.b16 %0, %1;" : "=r"(r) : "r"(a)); return r; }
template <bool ACC> __device__ __forceinline__ void mma16(float* d, uint32_t a0, uint32_t a1, uint32_t a2, uint32_t a3, uint32_t b0, uint32_t b1) {
  if (ACC) asm("mma.sync.aligned.m16n8k16.row.col.f32.bf16.bf16.f32 {%0,%1,%2,%3}, {%4,%5,%6,%7}, {%8,%9}, {%0,%1,%2,%3};"
               : "+f"(d[0]), "+f"(d[1]), "+f"(d[2]), "+f"(d[3]) : "r"(a0), "r"(a1), "r"(a2), "r"(a3), "r"(b0), "r"(b1));
  else asm("mma.sync.aligned.m16n8k16.row.col.f32.bf16.bf16.f32 {%0,%1,%2,%3}, {%4,%5,%6,%7}, {%8,%9}, {%10,%10,%10,%10};"
           : "=f"(d[0]), "=f"(d[1]), "=f"(d[2]), "=f"(d[3]) : "r"(a0), "r"(a1), "r"(a2), "r"(a3), "r"(b0), "r"(b1), "f"(0.f));
}
__device__ __forceinline__ uint32_t pin(uint32_t v) { uint32_t r; asm volatile("shfl.sync.bfly.b32 %0, %1, 0, 31, 0xffffffff;" : "=r"(r) : "r"(v)); return r; }
template <class T> __device__ __forceinline__ T* pin(T* p) {
  const uint64_t a = reinterpret_cast<uint64_t>(p);
  return reinterpret_cast<T*>((uint64_t)pin((uint32_t)a) | ((uint64_t)pin((uint32_t)(a >> 32)) << 32));
}
__device__ __forceinline__ uint32_t upin(uint32_t v) { return __shfl_sync(0xffffffffu, v, 0); }
template <class T> __device__ __forceinline__ T* upin(T* p) {
  const uint64_t a = reinterpret_cast<uint64_t>(p);
  return reinterpret_cast<T*>((uint64_t)upin((uint32_t)a) | ((uint64_t)upin((uint32_t)(a >> 32)) << 32));
}
__device__ __forceinline__ bool elect() {
  uint32_t p;
  asm volatile("{\n.reg .pred P;\nelect.sync _|P, 0xffffffff;\nselp.u32 %0, 1, 0, P;\n}" : "=r"(p));
  return p;
}
__device__ __forceinline__ uint32_t set_tag(uint32_t w, uint32_t tag) { uint32_t r; asm("lop3.b32 %0, %1, 0xfffffffe, %2, 0xea;" : "=r"(r) : "r"(w), "r"(tag)); return r; }
__device__ __forceinline__ uint32_t and_or(uint32_t w, uint32_t a, uint32_t o) { uint32_t r; asm("lop3.b32 %0, %1, %2, %3, 0xea;" : "=r"(r) : "r"(w), "r"(a), "r"(o)); return r; }
__device__ __forceinline__ uint32_t or3(uint32_t a, uint32_t b, uint32_t c) { uint32_t r; asm("lop3.b32 %0, %1, %2, %3, 0xfe;" : "=r"(r) : "r"(a), "r"(b), "r"(c)); return r; }
__device__ __forceinline__ uint32_t diff2(uint32_t a, uint32_t b, uint32_t tag) { uint32_t r; asm("lop3.b32 %0, %1, %2, %3, 0x7e;" : "=r"(r) : "r"(a), "r"(b), "r"(tag)); return r; }
__device__ __forceinline__ float2 cmul(float2 a, float2 b) { return make_float2(a.x * b.x - a.y * b.y, a.x * b.y + a.y * b.x); }

template<int TB> __device__ __forceinline__ void wgmma_ss_160_0(float (&d)[96], uint32_t al, uint32_t ah, uint32_t bl, uint32_t bh) {
  asm volatile("{\n.reg .b64 da, db;\nmov.b64 da, {%80, %81};\nmov.b64 db, {%82, %83};\n"
    "wgmma.mma_async.sync.aligned.m64n160k16.f32.bf16.bf16 {%0,%1,%2,%3,%4,%5,%6,%7,%8,%9,%10,%11,%12,%13,%14,%15,%16,%17,%18,%19,%20,%21,%22,%23,%24,%25,%26,%27,%28,%29,%30,%31,%32,%33,%34,%35,%36,%37,%38,%39,%40,%41,%42,%43,%44,%45,%46,%47,%48,%49,%50,%51,%52,%53,%54,%55,%56,%57,%58,%59,%60,%61,%62,%63,%64,%65,%66,%67,%68,%69,%70,%71,%72,%73,%74,%75,%76,%77,%78,%79}, da, db, 1, 1, 1, 1, %84;\n}\n"
    : "+f"(d[0]),"+f"(d[1]),"+f"(d[2]),"+f"(d[3]),"+f"(d[4]),"+f"(d[5]),"+f"(d[6]),"+f"(d[7]),"+f"(d[8]),"+f"(d[9]),"+f"(d[10]),"+f"(d[11]),"+f"(d[12]),"+f"(d[13]),"+f"(d[14]),"+f"(d[15]),"+f"(d[16]),"+f"(d[17]),"+f"(d[18]),"+f"(d[19]),"+f"(d[20]),"+f"(d[21]),"+f"(d[22]),"+f"(d[23]),"+f"(d[24]),"+f"(d[25]),"+f"(d[26]),"+f"(d[27]),"+f"(d[28]),"+f"(d[29]),"+f"(d[30]),"+f"(d[31]),"+f"(d[32]),"+f"(d[33]),"+f"(d[34]),"+f"(d[35]),"+f"(d[36]),"+f"(d[37]),"+f"(d[38]),"+f"(d[39]),"+f"(d[40]),"+f"(d[41]),"+f"(d[42]),"+f"(d[43]),"+f"(d[44]),"+f"(d[45]),"+f"(d[46]),"+f"(d[47]),"+f"(d[48]),"+f"(d[49]),"+f"(d[50]),"+f"(d[51]),"+f"(d[52]),"+f"(d[53]),"+f"(d[54]),"+f"(d[55]),"+f"(d[56]),"+f"(d[57]),"+f"(d[58]),"+f"(d[59]),"+f"(d[60]),"+f"(d[61]),"+f"(d[62]),"+f"(d[63]),"+f"(d[64]),"+f"(d[65]),"+f"(d[66]),"+f"(d[67]),"+f"(d[68]),"+f"(d[69]),"+f"(d[70]),"+f"(d[71]),"+f"(d[72]),"+f"(d[73]),"+f"(d[74]),"+f"(d[75]),"+f"(d[76]),"+f"(d[77]),"+f"(d[78]),"+f"(d[79])
    : "r"(al), "r"(ah), "r"(bl), "r"(bh), "n"(TB));
}
template<int TB> __device__ __forceinline__ void wgmma_ss_144_0(float (&d)[96], uint32_t al, uint32_t ah, uint32_t bl, uint32_t bh) {
  asm volatile("{\n.reg .b64 da, db;\nmov.b64 da, {%72, %73};\nmov.b64 db, {%74, %75};\n"
    "wgmma.mma_async.sync.aligned.m64n144k16.f32.bf16.bf16 {%0,%1,%2,%3,%4,%5,%6,%7,%8,%9,%10,%11,%12,%13,%14,%15,%16,%17,%18,%19,%20,%21,%22,%23,%24,%25,%26,%27,%28,%29,%30,%31,%32,%33,%34,%35,%36,%37,%38,%39,%40,%41,%42,%43,%44,%45,%46,%47,%48,%49,%50,%51,%52,%53,%54,%55,%56,%57,%58,%59,%60,%61,%62,%63,%64,%65,%66,%67,%68,%69,%70,%71}, da, db, 1, 1, 1, 1, %76;\n}\n"
    : "+f"(d[0]),"+f"(d[1]),"+f"(d[2]),"+f"(d[3]),"+f"(d[4]),"+f"(d[5]),"+f"(d[6]),"+f"(d[7]),"+f"(d[8]),"+f"(d[9]),"+f"(d[10]),"+f"(d[11]),"+f"(d[12]),"+f"(d[13]),"+f"(d[14]),"+f"(d[15]),"+f"(d[16]),"+f"(d[17]),"+f"(d[18]),"+f"(d[19]),"+f"(d[20]),"+f"(d[21]),"+f"(d[22]),"+f"(d[23]),"+f"(d[24]),"+f"(d[25]),"+f"(d[26]),"+f"(d[27]),"+f"(d[28]),"+f"(d[29]),"+f"(d[30]),"+f"(d[31]),"+f"(d[32]),"+f"(d[33]),"+f"(d[34]),"+f"(d[35]),"+f"(d[36]),"+f"(d[37]),"+f"(d[38]),"+f"(d[39]),"+f"(d[40]),"+f"(d[41]),"+f"(d[42]),"+f"(d[43]),"+f"(d[44]),"+f"(d[45]),"+f"(d[46]),"+f"(d[47]),"+f"(d[48]),"+f"(d[49]),"+f"(d[50]),"+f"(d[51]),"+f"(d[52]),"+f"(d[53]),"+f"(d[54]),"+f"(d[55]),"+f"(d[56]),"+f"(d[57]),"+f"(d[58]),"+f"(d[59]),"+f"(d[60]),"+f"(d[61]),"+f"(d[62]),"+f"(d[63]),"+f"(d[64]),"+f"(d[65]),"+f"(d[66]),"+f"(d[67]),"+f"(d[68]),"+f"(d[69]),"+f"(d[70]),"+f"(d[71])
    : "r"(al), "r"(ah), "r"(bl), "r"(bh), "n"(TB));
}
template<int TB> __device__ __forceinline__ void wgmma_ss_96_0(float (&d)[96], uint32_t al, uint32_t ah, uint32_t bl, uint32_t bh) {
  asm volatile("{\n.reg .b64 da, db;\nmov.b64 da, {%48, %49};\nmov.b64 db, {%50, %51};\n"
    "wgmma.mma_async.sync.aligned.m64n96k16.f32.bf16.bf16 {%0,%1,%2,%3,%4,%5,%6,%7,%8,%9,%10,%11,%12,%13,%14,%15,%16,%17,%18,%19,%20,%21,%22,%23,%24,%25,%26,%27,%28,%29,%30,%31,%32,%33,%34,%35,%36,%37,%38,%39,%40,%41,%42,%43,%44,%45,%46,%47}, da, db, 1, 1, 1, 1, %52;\n}\n"
    : "+f"(d[0]),"+f"(d[1]),"+f"(d[2]),"+f"(d[3]),"+f"(d[4]),"+f"(d[5]),"+f"(d[6]),"+f"(d[7]),"+f"(d[8]),"+f"(d[9]),"+f"(d[10]),"+f"(d[11]),"+f"(d[12]),"+f"(d[13]),"+f"(d[14]),"+f"(d[15]),"+f"(d[16]),"+f"(d[17]),"+f"(d[18]),"+f"(d[19]),"+f"(d[20]),"+f"(d[21]),"+f"(d[22]),"+f"(d[23]),"+f"(d[24]),"+f"(d[25]),"+f"(d[26]),"+f"(d[27]),"+f"(d[28]),"+f"(d[29]),"+f"(d[30]),"+f"(d[31]),"+f"(d[32]),"+f"(d[33]),"+f"(d[34]),"+f"(d[35]),"+f"(d[36]),"+f"(d[37]),"+f"(d[38]),"+f"(d[39]),"+f"(d[40]),"+f"(d[41]),"+f"(d[42]),"+f"(d[43]),"+f"(d[44]),"+f"(d[45]),"+f"(d[46]),"+f"(d[47])
    : "r"(al), "r"(ah), "r"(bl), "r"(bh), "n"(TB));
}
template<int TB> __device__ __forceinline__ void wgmma_ss_96_48(float (&d)[96], uint32_t al, uint32_t ah, uint32_t bl, uint32_t bh) {
  asm volatile("{\n.reg .b64 da, db;\nmov.b64 da, {%48, %49};\nmov.b64 db, {%50, %51};\n"
    "wgmma.mma_async.sync.aligned.m64n96k16.f32.bf16.bf16 {%0,%1,%2,%3,%4,%5,%6,%7,%8,%9,%10,%11,%12,%13,%14,%15,%16,%17,%18,%19,%20,%21,%22,%23,%24,%25,%26,%27,%28,%29,%30,%31,%32,%33,%34,%35,%36,%37,%38,%39,%40,%41,%42,%43,%44,%45,%46,%47}, da, db, 1, 1, 1, 1, %52;\n}\n"
    : "+f"(d[48]),"+f"(d[49]),"+f"(d[50]),"+f"(d[51]),"+f"(d[52]),"+f"(d[53]),"+f"(d[54]),"+f"(d[55]),"+f"(d[56]),"+f"(d[57]),"+f"(d[58]),"+f"(d[59]),"+f"(d[60]),"+f"(d[61]),"+f"(d[62]),"+f"(d[63]),"+f"(d[64]),"+f"(d[65]),"+f"(d[66]),"+f"(d[67]),"+f"(d[68]),"+f"(d[69]),"+f"(d[70]),"+f"(d[71]),"+f"(d[72]),"+f"(d[73]),"+f"(d[74]),"+f"(d[75]),"+f"(d[76]),"+f"(d[77]),"+f"(d[78]),"+f"(d[79]),"+f"(d[80]),"+f"(d[81]),"+f"(d[82]),"+f"(d[83]),"+f"(d[84]),"+f"(d[85]),"+f"(d[86]),"+f"(d[87]),"+f"(d[88]),"+f"(d[89]),"+f"(d[90]),"+f"(d[91]),"+f"(d[92]),"+f"(d[93]),"+f"(d[94]),"+f"(d[95])
    : "r"(al), "r"(ah), "r"(bl), "r"(bh), "n"(TB));
}
__device__ __forceinline__ void wgmma_rs_72(float (&d)[36], uint32_t a0, uint32_t a1, uint32_t a2, uint32_t a3, uint32_t bl, uint32_t bh, int sd) {
  asm volatile("{\n.reg .pred p;\n.reg .b64 db;\nsetp.ne.b32 p, %42, 0;\nmov.b64 db, {%40, %41};\n"
    "wgmma.mma_async.sync.aligned.m64n72k16.f32.bf16.bf16 {%0,%1,%2,%3,%4,%5,%6,%7,%8,%9,%10,%11,%12,%13,%14,%15,%16,%17,%18,%19,%20,%21,%22,%23,%24,%25,%26,%27,%28,%29,%30,%31,%32,%33,%34,%35}, {%36,%37,%38,%39}, db, p, 1, 1, 1;\n}\n"
    : "+f"(d[0]),"+f"(d[1]),"+f"(d[2]),"+f"(d[3]),"+f"(d[4]),"+f"(d[5]),"+f"(d[6]),"+f"(d[7]),"+f"(d[8]),"+f"(d[9]),"+f"(d[10]),"+f"(d[11]),"+f"(d[12]),"+f"(d[13]),"+f"(d[14]),"+f"(d[15]),"+f"(d[16]),"+f"(d[17]),"+f"(d[18]),"+f"(d[19]),"+f"(d[20]),"+f"(d[21]),"+f"(d[22]),"+f"(d[23]),"+f"(d[24]),"+f"(d[25]),"+f"(d[26]),"+f"(d[27]),"+f"(d[28]),"+f"(d[29]),"+f"(d[30]),"+f"(d[31]),"+f"(d[32]),"+f"(d[33]),"+f"(d[34]),"+f"(d[35])
    : "r"(a0), "r"(a1), "r"(a2), "r"(a3), "r"(bl), "r"(bh), "r"(sd));
}
__device__ __forceinline__ void wgmma_rs_48(float (&d)[24], uint32_t a0, uint32_t a1, uint32_t a2, uint32_t a3, uint32_t bl, uint32_t bh, int sd) {
  asm volatile("{\n.reg .pred p;\n.reg .b64 db;\nsetp.ne.b32 p, %30, 0;\nmov.b64 db, {%28, %29};\n"
    "wgmma.mma_async.sync.aligned.m64n48k16.f32.bf16.bf16 {%0,%1,%2,%3,%4,%5,%6,%7,%8,%9,%10,%11,%12,%13,%14,%15,%16,%17,%18,%19,%20,%21,%22,%23}, {%24,%25,%26,%27}, db, p, 1, 1, 1;\n}\n"
    : "+f"(d[0]),"+f"(d[1]),"+f"(d[2]),"+f"(d[3]),"+f"(d[4]),"+f"(d[5]),"+f"(d[6]),"+f"(d[7]),"+f"(d[8]),"+f"(d[9]),"+f"(d[10]),"+f"(d[11]),"+f"(d[12]),"+f"(d[13]),"+f"(d[14]),"+f"(d[15]),"+f"(d[16]),"+f"(d[17]),"+f"(d[18]),"+f"(d[19]),"+f"(d[20]),"+f"(d[21]),"+f"(d[22]),"+f"(d[23])
    : "r"(a0), "r"(a1), "r"(a2), "r"(a3), "r"(bl), "r"(bh), "r"(sd));
}
template<int N,int OFF,int TB> __device__ __forceinline__ void wgmma_ss(float (&d)[96], uint32_t al, uint32_t ah, uint32_t bl, uint32_t bh) {
  if constexpr (N==160 && OFF==0) wgmma_ss_160_0<TB>(d, al, ah, bl, bh);
  else if constexpr (N==144 && OFF==0) wgmma_ss_144_0<TB>(d, al, ah, bl, bh);
  else if constexpr (N==96 && OFF==0) wgmma_ss_96_0<TB>(d, al, ah, bl, bh);
  else if constexpr (N==96 && OFF==48) wgmma_ss_96_48<TB>(d, al, ah, bl, bh);
}

__device__ __forceinline__ void dft3(float2& a, float2& b, float2& c) {
  const float s = 0.86602540378443864676f;
  float2 t = make_float2(b.x + c.x, b.y + c.y), d = make_float2(b.x - c.x, b.y - c.y);
  float2 m = make_float2(fmaf(-0.5f, t.x, a.x), fmaf(-0.5f, t.y, a.y));
  a = make_float2(a.x + t.x, a.y + t.y);
  b = make_float2(fmaf(s, d.y, m.x), fmaf(-s, d.x, m.y));
  c = make_float2(fmaf(-s, d.y, m.x), fmaf(s, d.x, m.y));
}
__device__ __forceinline__ void dft9(float2 (&x)[9]) {
  const float2 w1 = make_float2(0.76604444311897803520f, -0.64278760968653932632f);
  const float2 w2 = make_float2(0.17364817766693034885f, -0.98480775301220805937f);
  const float2 w4 = make_float2(-0.93969262078590838405f, -0.34202014332566873304f);
  dft3(x[0], x[3], x[6]); dft3(x[1], x[4], x[7]); dft3(x[2], x[5], x[8]);
  x[4] = cmul(x[4], w1); x[7] = cmul(x[7], w2); x[5] = cmul(x[5], w2); x[8] = cmul(x[8], w4);
  dft3(x[0], x[1], x[2]); dft3(x[3], x[4], x[5]); dft3(x[6], x[7], x[8]);
  float2 t;
  t = x[1]; x[1] = x[3]; x[3] = t;
  t = x[2]; x[2] = x[6]; x[6] = t;
  t = x[5]; x[5] = x[7]; x[7] = t;
}

__device__ __forceinline__ uint32_t* mod_ptr(Scratch* sc, int u, int t128) {
  const int i = t128 & 15;
  return u < 72 ? sc->moda + (t128 >> 4) * (2 * D_) + 16 * u + 2 * (i & 7) + (i >> 3) : sc->mod + 16 * (u - 72) + i;
}
__device__ __forceinline__ void mod_unit(Scratch* sc, int u, int t128, uint32_t sw_, uint32_t bar, int ph, uint32_t rb, uint32_t tag) {
  const int w = t128 >> 5, l = t128 & 31;
  uint32_t b[18];
#pragma unroll
  for (int i = 0; i < 18; i++) b[i] = lds(red + 512 + (72 * w + 4 * i + (l & 3)) * 4);
  const uint32_t sa = pin(sw_ + (144 * w + (l & 7) + 8 * (l >> 4)) * 32 + (((l >> 3) ^ (l >> 2)) & 1) * 16);
  const uint32_t sr = pin(rb + (l >> 2) * 16 + w * 4);
  uint32_t* const dst = pin(mod_ptr(sc, u, t128));
  const int kind = u / 36;
  const float mul = __uint_as_float(pin(__float_as_uint(kind == 0 ? 16.0f : 1.0f))), add = __uint_as_float(pin(__float_as_uint(kind == 1 || kind == 4 ? 1.0f : 0.0f)));
  mbar_wait(bar, ph);
  if (t128 == 0 && u < 72) TS(10);
  float d[3][4];
#pragma unroll
  for (int i = 0; i < 9; i++) {
    uint32_t a0, a1, a2, a3;
    asm volatile("ldmatrix.sync.aligned.m8n8.x4.trans.shared.b16 {%0,%1,%2,%3}, [%4];" : "=r"(a0), "=r"(a1), "=r"(a2), "=r"(a3) : "r"(sa + i * 512) : "memory");
    if (i < 3) mma16<false>(d[i], a0, a1, a2, a3, b[2 * i], b[2 * i + 1]);
    else mma16<true>(d[i % 3], a0, a1, a2, a3, b[2 * i], b[2 * i + 1]);
  }
  if ((l & 3) == 0) { sts(sr, __float_as_uint(d[0][0] + d[1][0] + d[2][0])); sts(sr + 128, __float_as_uint(d[0][2] + d[1][2] + d[2][2])); }
  bar_sync(4, 128);
  const uint4 v = lds4(rb + (l & 15) * 16);
  const float m = rbf(fmaf(rbf((__uint_as_float(v.x) + __uint_as_float(v.y)) + (__uint_as_float(v.z) + __uint_as_float(v.w))), mul, add));
  if (u < 72 || t128 < 16) *dst = __float_as_uint(m) | tag;
}

__device__ __forceinline__ float rsq(float x) { float r; asm("rsqrt.approx.ftz.f32 %0, %1;" : "=f"(r) : "f"(x)); return r; }
__device__ __forceinline__ void ln_stats2(const float (&a)[18], const float (&b)[18], float sc, float& oa, float& ra, float& ob, float& rb) {
  float v[4] = {0.f, 0.f, 0.f, 0.f}, w[4] = {0.f, 0.f, 0.f, 0.f};
#pragma unroll
  for (int i = 0; i < 18; i += 2) {
    v[0] += a[i]; v[1] = fmaf(a[i], a[i], v[1]); v[2] += b[i]; v[3] = fmaf(b[i], b[i], v[3]);
    w[0] += a[i + 1]; w[1] = fmaf(a[i + 1], a[i + 1], w[1]); w[2] += b[i + 1]; w[3] = fmaf(b[i + 1], b[i + 1], w[3]);
  }
#pragma unroll
  for (int e = 0; e < 4; e++) v[e] += w[e];
#pragma unroll
  for (int o = 16; o; o >>= 1) {
#pragma unroll
    for (int e = 0; e < 4; e++) v[e] += __shfl_xor_sync(0xffffffffu, v[e], o);
  }
  const float ma = v[0] * (1.0f / D_), mb = v[2] * (1.0f / D_);
  ra = sc * rsq(fmaxf(fmaf(-ma, ma, v[1] * (1.0f / D_)), 0.f) + 1e-5f);
  rb = sc * rsq(fmaxf(fmaf(-mb, mb, v[3] * (1.0f / D_)), 0.f) + 1e-5f);
  oa = -ma * ra; ob = -mb * rb;
}

__device__ __forceinline__ float tmat(int c, int q, int j) {
  const int ph = q == 1 ? 1024 * j : (q >> 1) * (c + 128 * j) + 512 * (q & 1);
  return __cosf((float)(((ph + 1024) & 2047) - 1024) * (6.283185307179586f / 2048.0f));
}
__device__ __forceinline__ uint32_t line_off(int k1, int kap, int pi, int f) {
  int kd = 64 * k1 + 9 * kap;
  if (kap == 0 && k1 > 4) kd -= 288;
  if (kd >= D_) kd -= D_;
  return pi * 2400 + ((min(kd, D_ - kd) ^ f) << 3);
}

constexpr int JSK = 5;
struct Ring { uint32_t st, ph; };
template <bool G2, class T> __device__ __forceinline__ void ring_next(T& st, T& ph) {
  if (++st == NST) st = 0;
  ph ^= ((G2 ? 0xDu : 0x1u) >> st) & 1;
}
__device__ __forceinline__ void arrive_if(uint32_t a, uint32_t p) {
  asm volatile("{\n.reg .pred p;\nsetp.ne.u32 p, %1, 0;\n@p mbarrier.arrive.shared::cta.b64 _, [%0];\n}" ::"r"(a), "r"(p) : "memory");
}
template <int NA> __device__ __forceinline__ void reg_fence_n(float (&d)[96]) {
#pragma unroll
  for (int i = 0; i < NA; i++) asm volatile("" : "+f"(d[i])::"memory");
}
template <int MODE>
__device__ __forceinline__ void gemm_main(float (&acc)[96], uint32_t da0, uint32_t da1, uint32_t db0, int wg, Ring& rg,
                                          uint32_t* x1p, const uint32_t (&xr)[18]) {
  static_assert(JSK == NST - 1, "the held slot is the first one that is not refilled by GEMM1");
  constexpr int NKB = MODE == 3 ? 36 : 32;
  constexpr uint32_t HA = 0x40000040u, HB = MODE == 3 ? 0x40000040u : 0x80000020u;
  constexpr uint32_t KA = 2048 >> 4, KB = MODE == 3 ? (32 >> 4) : (1024 >> 4);
  constexpr int NA = MODE == 3 ? 72 : MODE == 1 ? 96 : 80;
  const uint32_t t = threadIdx.x & 127;
  const uint32_t eb = full0 + 8 * NST;
  uint32_t pb = 0, rel = t == 0, prel = 0, ok = 0;
  int n = MODE == 3 ? NKB - JSK : X1K + 2 * wg;
#pragma unroll 1
  for (int pass = MODE == 3 ? 0 : -1;; pass++) {
#pragma unroll 1
    do {
      const uint32_t so = rg.st * ((MODE == 3 ? STAGE2 : STAGE) >> 4), cb = eb + 8 * rg.st;
      if (__builtin_expect(!ok, 0)) mbar_wait(full0 + 8 * rg.st, rg.ph);
      reg_fence_n<NA>(acc);
      if (MODE == 1 && wg) {
        wg_fence();
#pragma unroll
        for (int k = 0; k < 4; k++) wgmma_ss<96, 48, 1>(acc, da1 + so + k * KA, HA, db0 + so + k * KB, HB);
        wg_commit();
      }
      wg_fence();
#pragma unroll
      for (int k = 0; k < 4; k++) {
        if (k == 3) { ring_next<MODE == 3>(rg.st, rg.ph); ok = PEEK ? mbar_test(full0 + 8 * rg.st, rg.ph) : 0; }
        if (MODE == 0) wgmma_ss<160, 0, 1>(acc, da0 + so + k * KA, HA, db0 + so + k * KB, HB);
        else if (MODE == 3) wgmma_ss<144, 0, 0>(acc, da0 + so + k * KA, HA, db0 + so + k * KB, HB);
        else wgmma_ss<96, 0, 1>(acc, da0 + so + k * KA, HA, db0 + so + k * KB, HB);
      }
      wg_commit();
      wg_wait<1>();
      reg_fence_n<NA>(acc);
      arrive_if(pb, prel);
      pb = cb; prel = rel;
    } while (--n);
    if (pass == 2 - wg) break;
    if (MODE != 3 && pass < 0) {
      if (blockIdx.x < 128) {
#pragma unroll
        for (int i = 0; i < 9; i++) { x1p[32 * i] = xr[i]; x1p[128 * 288 + 32 * i] = xr[9 + i]; }
      }
      n = NKB - JSK - X1K - 2 * wg;
      continue;
    }
    n = 1;
    if (pass == 0) {
      if (MODE != 3) prel = rel & wg;
      else prel = rel = 0;
      n = JSK - 1 + wg;
      if (!wg) continue;
      wg_wait<0>();
      arrive_if(pb, prel);
      prel = 0;
    }
    bar_sync(1, 256);
  }
  wg_wait<0>();
  reg_fence_n<NA>(acc);
  if (MODE != 3) arrive_if(pb, MODE == 1 ? prel & ~wg : prel);
}

constexpr float GK1 = 2.0f * 0.7978845608028654f, GK3 = 8.0f * 0.044715f * 0.7978845608028654f;

__device__ __forceinline__ int kb2_order(int i) { const int wv = i / 6; return 6 * (i - 6 * wv) + ((0x431250 >> (4 * wv)) & 7); }

__device__ __forceinline__ void wait_flags(const unsigned* base, int n, int idx, unsigned target, uint64_t& ready) {
  if ((ready >> idx) & 1) return;
  const int l = threadIdx.x & 31;
  int it = 0;
  while (true) {
    unsigned a = ld_rlx(base + l), b = l + 32 < n ? ld_rlx(base + l + 32) : target;
    ready = (uint64_t)__ballot_sync(0xffffffffu, (int)(a - target) >= 0) | ((uint64_t)__ballot_sync(0xffffffffu, (int)(b - target) >= 0) << 32);
    if (((ready >> idx) & 1) || ++it > SPIN_MAX) break;
  }
}

enum { B_FULL = 0, B_EMPTY = 6, B_S4 = 12, B_S5, B_LAND, B_FLT = B_LAND + 6, B_Z1, B_Z2, B_GO, B_X, B_WM, B_NUM, B_W0 = B_NUM };

__global__ void __launch_bounds__(NTHR, 1)
fused_kernel(const Params p, const __grid_constant__ Maps maps) {
  extern __shared__ __align__(1024) uint8_t smem_raw[];
  const int tid = threadIdx.x, cta = blockIdx.x, t128 = tid & 127;
  const int wp = __shfl_sync(0xffffffffu, tid >> 5, 0), wg = wp >> 2;
  const int l = tid & 31, g = l >> 2, t = l & 3;
  Scratch* const sc = p.s;
  const bool rows = cta < 128;
  const int R = cta - 12;

  uint32_t xr[18];
  uint32_t cv[3];
  const unsigned ep = ld_rlx(&sc->cnt[C_EP]) + 1;
  if (tid == 0) TS(0);
  if (wg == 2) {
#pragma unroll
    for (int i = 0; i < 3; i++) cv[i] = ld_nc(reinterpret_cast<const uint32_t*>(p.c) + min(t128 + 128 * i, 287));
    if (wp == 9 && l < 9 && rows) {
      const int h = 9 * cta + l;
      prefetch_l2(reinterpret_cast<const uint8_t*>(p.wmod) + (size_t)(h >> 1) * (12 * D_) + (h & 1) * (2 * D_), 2 * D_);
    }
    if (tid == 256 && cta < 72) {
      mbar_init(full0 + 8 * B_W0, 1);
      fence_async_smem();
      mbar_expect(full0 + 8 * B_W0, 18432);
#pragma unroll 1
      for (int i = 0; i < 3; i++) tma2d(sbase + O_P2 + i * 6144, &maps.wm, 16 * cta, 192 * i, full0 + 8 * B_W0);
    }
    __syncwarp();
#pragma unroll 1
    for (int u = cta < 72 ? cta : 72 + cta; u < 216; u += u < 72 ? 72 : NCTA) if (u < 72 || t128 < 16) *mod_ptr(sc, u, t128) = 0;
    if (wp == 11 && smem_u32(smem_raw) != sbase) __trap();
    if (wp >= 10 && elect()) {
#pragma unroll 1
      for (int i = wp - 10; i < B_NUM; i += 2) mbar_init(full0 + 8 * i, i == B_FLT ? 4 : i == B_WM ? 3 : i < B_LAND ? 2 : 1);
      fence_async_smem();
    }
    __syncwarp();
  }
  CK(0);
  auto load_x = [&]() {
    const uint32_t* xs = reinterpret_cast<const uint32_t*>(p.x) + (size_t)(cta + 256 * wp) * 288 + l;
#pragma unroll
    for (int i = 0; i < 9; i++) { xr[i] = ld_nc(xs + 32 * i); xr[9 + i] = ld_nc(xs + 128 * 288 + 32 * i); }
  };
  if (rows && wg < 2) load_x();
  if (tid == 64 && cta == NCTA - 1) prefetch_l2(p.tab, sizeof(T_TAB));
  __syncwarp();
  const uint32_t tag16 = (ep & 0x7fffu) | 0x8000u, tag1 = ep & 1u;

  if (wg == 2) {
#pragma unroll
    for (int i = 0; i < 3; i++) {
      const float c0 = bf_lo(cv[i]), c1 = bf_hi(cv[i]);
      sts(red + 512 + min(t128 + 128 * i, 287) * 4, pack_bf16(__fdividef(c0, 1.0f + __expf(-c0)), __fdividef(c1, 1.0f + __expf(-c1))));
    }
    if (wp == 9 && l < 13) asm volatile("prefetch.tensormap [%0];" ::"l"(&maps.z1 + l) : "memory");
    bar_sync(4, 128);
    if (cta < 72) {
      mod_unit(sc, cta, t128, sbase + O_P2, full0 + 8 * B_W0, 0, red, tag16);
      if (t128 == 0) TS(25);
    }
    CK(1);
  }
  const int pi = R / 15, col0 = 20 * (R - 15 * pi);
  const int xu = DF_ * pi + col0, xv = DF_ * (pi ? 16 - pi : 8) + col0;
  auto load_filter = [&](int a) {
    const int x = (a & 1) ? xv : xu;
    const bool wide = (x & 15) > 12;
    mbar_expect(full0 + 8 * B_FLT, wide ? 12288 : 8192);
    tma2d(sbase + O_RAW + a * 12288, &maps.wf[a & 2], x & ~15, 0, full0 + 8 * B_FLT);
    if (wide) tma2d(sbase + O_RAW + a * 12288 + 8192, &maps.wf[(a & 2) + 1], (x & ~15) + 32, 0, full0 + 8 * B_FLT);
  };
  const int kap = 8 * ((wp & 3) ^ (wg & 1)) + g;
  uint4 af[4];
  if (rows) {
    uint32_t tb[4];
#pragma unroll
    for (int i = 0; i < 4; i++) tb[i] = pack_bf16(tmat(cta, 8 * (i >> 1) + g, 2 * t + 8 * (i & 1)), tmat(cta, 8 * (i >> 1) + g, 2 * t + 8 * (i & 1) + 1));
    uint32_t sb1[3], lo[9];
#pragma unroll
    for (int i = 0; i < 4; i++) tb[i] = pin(tb[i]);
#pragma unroll
    for (int i = 0; i < 3; i++) {
      const int d = 48 * wp + 16 * i + (l & 15);
      sb1[i] = pin(sbase + O_B1 + (l >> 4) * 9216 + (d % 9) * 1024 + (d & 63) * 16);
    }
    const uint32_t snt = pin(sbase + O_NRM + ((l & 7) + 8 * (l >> 4)) * 1168 + (48 * wp + (l & 8)) * 2);
    uint2 ms[3], mc[3];
    const uint32_t smask = pin(t ? 0u : 0xffff0000u);
    const uint32_t* const mp = pin(sc->moda + (cta >> 4) * (2 * D_) + 48 * wp + 2 * g);
    auto load_mod = [&]() {
#pragma unroll
      for (int i = 0; i < 3; i++) { ms[i] = ld_rlx2(mp + 16 * i); mc[i] = ld_rlx2(mp + D_ + 16 * i); }
    };
    if (wg < 2) {
#pragma unroll
      for (int k1 = 0; k1 < 9; k1++) lo[k1] = pin(sbase + O_Z1 + line_off(k1, kap, 4 * wg + t, cta & 3));
      float a[18], b[18];
#pragma unroll
      for (int i = 0; i < 9; i++) { a[2 * i] = bf_lo(xr[i]); a[2 * i + 1] = bf_hi(xr[i]); b[2 * i] = bf_lo(xr[9 + i]); b[2 * i + 1] = bf_hi(xr[9 + i]); }
      float oa, ra, ob, rb;
      ln_stats2(a, b, 1.0f, oa, ra, ob, rb);
      CK(1);
      const uint32_t sn = sbase + O_NRM + wp * 2336 + l * 4;
#pragma unroll
      for (int i = 0; i < 9; i++) {
        sts(sn + i * 128, pack_bf16(fmaf(a[2 * i], ra, oa), fmaf(a[2 * i + 1], ra, oa)));
        sts(sn + 1168 + i * 128, pack_bf16(fmaf(b[2 * i], rb, ob), fmaf(b[2 * i + 1], rb, ob)));
      }
      CK(2);
      bar_arrive(10, NTHR);
      load_mod();
#pragma unroll
      for (int kk = 0; kk < 4; kk++) af[kk] = ld_nc4(p.tab + TB_F + kk * 128 + (t128 ^ (wg << 5)));
      bar_sync(1, 256);
      if (tid == 0) TS(2);
    } else {
      bar_sync(10, NTHR);
      load_mod();
      CK(2);
      if (PFF && wp >= 12 - PFF && elect()) prefetch_l2(reinterpret_cast<const uint8_t*>(wp == 10 ? p.wr : p.wi) + cta * 9248, 9248);
      __syncwarp();
    }
    float rs[3][8];
#pragma unroll
    for (int i = 0; i < 3; i++) {
      uint32_t a0, a1, a2, a3;
      asm volatile("ldmatrix.sync.aligned.m8n8.x4.trans.shared.b16 {%0,%1,%2,%3}, [%4];" : "=r"(a0), "=r"(a1), "=r"(a2), "=r"(a3)
                   : "r"(snt + 32 * i) : "memory");
      mma16<false>(&rs[i][0], a0, a1, a2, a3, tb[0], tb[1]);
      mma16<false>(&rs[i][4], a0, a1, a2, a3, tb[2], tb[3]);
    }
    CK(3);
    {
      int it = 0;
#pragma unroll 1
      while (true) {
        uint32_t bad = 0;
#pragma unroll
        for (int i = 0; i < 3; i++) bad |= diff2(ms[i].x, ms[i].y, tag16) | diff2(mc[i].x, mc[i].y, tag16);
        if (!any(bad & 0xffffu) || ++it > SPIN_MAX) break;
        load_mod();
      }
      CK(4);
      if (tid == 0) TS(3);
#pragma unroll
      for (int i = 0; i < 3; i++) {
        const float c0 = bf_hi(mc[i].x), c1 = bf_hi(mc[i].y);
        const float s0 = __uint_as_float(ms[i].x & smask), s1 = __uint_as_float(ms[i].y & smask);
        stmatrix4(sb1[i], pack_bf16(fmaf(rs[i][0], c0, s0), rs[i][1] * c0), pack_bf16(fmaf(rs[i][2], c1, s1), rs[i][3] * c1),
                  pack_bf16(rs[i][4] * c0, rs[i][5] * c0), pack_bf16(rs[i][6] * c1, rs[i][7] * c1));
      }
    }
    fence_async_smem();
    CK(5);
    if (wg == 2) {
      bar_arrive(5, NTHR);
      if (R >= 0 && elect()) load_filter(wp - 8);
      __syncwarp();
    } else {
      bar_sync(5, NTHR);
      CK(6);
      float acc[36];
      const uint32_t db = (((sbase + O_B1 + wg * 9216) & 0x3FFFF) >> 4) | ((128 >> 4) << 16);
      wg_fence();
#pragma unroll
      for (int kk = 0; kk < 4; kk++) wgmma_rs_72(acc, af[kk].x, af[kk].y, af[kk].z, af[kk].w, db + kk * 16, 1024 >> 4, kk);
      wg_commit();
      wg_wait<0>();
      reg_fence(acc);
      CK(7);
      float2 za[9], zb[9];
#pragma unroll
      for (int i = 0; i < 9; i++) { za[i] = make_float2(acc[4 * i], acc[4 * i + 2]); zb[i] = make_float2(acc[4 * i + 1], acc[4 * i + 3]); }
      dft9(za); dft9(zb);
      if (kap == 0) {
#pragma unroll
        for (int k = 1; k < 5; k++) {
          float2 a = za[k], b = za[9 - k];
          za[k] = make_float2(a.x + b.x, a.y - b.y); za[9 - k] = make_float2(a.y + b.y, b.x - a.x);
          a = zb[k]; b = zb[9 - k];
          zb[k] = make_float2(a.x + b.x, a.y - b.y); zb[9 - k] = make_float2(a.y + b.y, b.x - a.x);
        }
        sts2(lo[0] + 288 * 8, set_tag(pack_bf16(za[0].y, 0.f), tag1), pack_bf16(zb[0].y, 0.f));
        za[0].y = 0.f; zb[0].y = 0.f;
      }
      __syncwarp();
#pragma unroll
      for (int k1 = 0; k1 < 9; k1++) sts2(lo[k1], set_tag(pack_bf16(za[k1].x, za[k1].y), tag1), pack_bf16(zb[k1].x, zb[k1].y));
      fence_async_smem();
      CK(8);
      bar_arrive(2 + wg, 160);
      {
        const uint32_t fx = (((cta >> 4) ^ cta) & 3) << 3, dl = O_IN - O_Z1, st = sbase + O_ST + 15360 + tid * 16;
        sts4(st, (lo[0] ^ fx) + dl, (lo[1] ^ fx) + dl, (lo[2] ^ fx) + dl, (lo[3] ^ fx) + dl);
        sts4(st + 4096, (lo[4] ^ fx) + dl, (lo[5] ^ fx) + dl, (lo[6] ^ fx) + dl, (lo[7] ^ fx) + dl);
        sts4(st + 8192, (lo[8] ^ fx) + dl, (lo[0] ^ fx) + dl + (kap ? 0 : 288 * 8),
             sbase + O_B3 + wg * 1024 + (l >> 4) * 2048 + (2 * (kap & 24) + (l & 15)) * 16, 0);
      }
    }
    {
      uint32_t sy[6];
#pragma unroll
      for (int i = 0; i < 6; i++) {
        const int rr = 16 * (wp & 3) + g + 8 * (i & 1);
        sy[i] = sbase + O_Y + (t * 584 + 64 * ((3 * wg + (i >> 1) + 63 - rr) % 9) + rr) * 4;
      }
      sts4(sbase + O_ST + tid * 16, movm(tb[0]), movm(tb[2]), movm(tb[1]), movm(tb[3]));
      sts4(sbase + O_ST + 6144 + tid * 16, sy[0], sy[1], sy[2], sy[3]);
      sts2(sbase + O_ST + 12288 + tid * 8, sy[4], sy[5]);
    }
  } else {
    __syncthreads();
  }

  if ((wp >> 1) == 4) {
    if (rows) {
      const int slot = 4 * (cta & 7) + ((cta >> 4) & 3) + 32 * (2 * (cta >> 6) + ((cta >> 3) & 1));
      const uint32_t c0 = upin(40 * slot), c1 = upin(60 * (wp - 8)), src = upin(sbase + O_Z1 + (wp - 8) * 9600);
      const CUtensorMap* mp = upin(&maps.z1);
      unsigned* hint = pin(&sc->cnt[C_Z1 + 32 * (wp - 8)]);
      bar_sync(wp - 6, 160);
      if (elect()) {
        tma_st2d(mp, src, c0, c1);
        HW();
        red_add(hint, 1);
        if (wp == 8) TS(4);
      }
    } else {
      int it = 0;
      while (any((ld_rlx(sc->moda + 36 * l) ^ tag16) & 0xffffu) && ++it < SPIN_MAX) {}
      if (elect()) { load_filter(wp - 8); load_filter(wp - 6); }
    }
    __syncwarp();
  }
  auto load_wm = [&](int u) {
    if (wp > 8 && elect()) {
      mbar_expect(full0 + 8 * B_WM, 6144);
      tma2d(sbase + O_NRM + (wp - 9) * 6144, &maps.wm, 16 * u, 192 * (wp - 9), full0 + 8 * B_WM);
    }
    __syncwarp();
  };
  if (R >= 0) {
    const int nl = (col0 + wp < DF_) + (wg < 2 && col0 + wp + 12 < DF_);
    uint4 cf[2][4], G[4];
#pragma unroll
    for (int i = 0; i < 4; i++) {
      cf[0][i] = __ldg(p.tab + TB_P2 + i * 32 + l);
      cf[1][i] = __ldg(p.tab + TB_P2 + (pi ? i : 4 + i) * 32 + l);
      G[i] = __ldg(p.tab + TB_P2 + (8 + i) * 32 + l);
    }
    const uint32_t* zin = sc->z1 + (size_t)R * 5120;
    if (wp == 10) {
      const uint32_t* zu = upin(zin);
      if (elect()) mbar_expect(full0 + 8 * B_Z1, 20480);
      wait_cnt(&sc->cnt[C_Z1 + 32 * (pi >> 2)], 128 * ep);
      if (elect()) {
        bulk_ld(sbase + O_P2, zu, 20480, full0 + 8 * B_Z1);
        TS(12);
      }
      __syncwarp();
    }
    mbar_wait(full0 + 8 * B_FLT, 0);
    CK(9);
    float wn[16], wc[16];
#pragma unroll 1
    for (int ln = nl - 1; ln >= 0; ln--) {
      const int col = col0 + wp + 12 * ln, k2 = (57 * col) & 63;
      const bool cj = k2 > 32 || (k2 == 32 && col != 288);
      const float nr = ((col & 31) == 0 && col != 0 && col != 288 ? 0.5f : 1.0f) / ((float)S_ * D_), ni = cj ? -nr : nr;
#pragma unroll
      for (int i = 0; i < 16; i++) wn[i] = wc[i];
#pragma unroll
      for (int cl = 0; cl < 2; cl++) {
        const int v = cl ^ (cj && pi), e = ((v ? xv : xu) & 15) + wp + 12 * ln, sh = e < 32 ? 6 : 5;
        const uint32_t base = sbase + O_RAW + v * 12288 + (e < 32 ? 2 * e : 8192 - 64 + 2 * e), msk = e < 32 ? 0x30 : 0x10;
        const int dm = v ? (cj || pi ? -1 : 0) : 0;
#pragma unroll
        for (int tt = 0; tt < 4; tt++) {
          const int kc = g + 64 * (tt >> 1) + 16 * t + 8 * (tt & 1);
          uint32_t a = base + ((((cj ? -kc : kc) + dm) & 127) << sh);
          a ^= (a >> 3) & msk;
          wc[4 * tt + 2 * cl] = lds_bf(a) * nr; wc[4 * tt + 2 * cl + 1] = lds_bf(a + 24576) * ni;
        }
      }
    }
    const float al = __uint_as_float(pin((pi ? 0x3f800000u : 0u) + (l >> 5)));
    const uint32_t tagv = pin(tag1 + (l >> 5));
    CK(10);
    uint32_t off = pin(l * 160 + ((wp ^ (g & 3)) << 3));
    uint32_t offo = pin(sbase + O_P2 + 20480 + off - 64 * l), po = 3072;
    unsigned* hz2 = pin(&sc->cnt[C_Z2]);
    const uint32_t do2 = pin(12288 - 32 * l);
    const CUtensorMap* mz2 = upin(&maps.z2[wp == 0]);
    const uint32_t sz2 = upin(sbase + O_P2 + 20480 + (wp ? 0 : 12288)), cz2 = upin(40 * R + (wp ? 0 : 24));
    mbar_wait(full0 + 8 * B_Z1, 0);
    CK(11);
    if (tid == 0) TS(8);
    if (wg == 2) load_wm(72 + cta);
    uint2 v[4], v2[4];
    const uint32_t o2 = nl > 1 ? 96 : 0;
#pragma unroll
    for (int i = 0; i < 4; i++) { v[i] = lds2(sbase + O_P2 + off + i * 5120); v2[i] = lds2(sbase + O_P2 + off + o2 + i * 5120); }
    auto bad2 = [&]() {
      return any(or3(or3(diff2(v[0].x, v[1].x, tagv), diff2(v[2].x, v[3].x, tagv), diff2(v2[0].x, v2[1].x, tagv)), diff2(v2[2].x, v2[3].x, tagv), 0) & 1);
    };
    if (__builtin_expect(bad2() && nl, 0)) {
      FAILCNT(0);
      int it = 0;
      do {
#pragma unroll
        for (int i = 0; i < 4; i++) {
          v[i] = ld_rlx2(reinterpret_cast<const uint8_t*>(zin) + off + i * 5120);
          v2[i] = ld_rlx2(reinterpret_cast<const uint8_t*>(zin) + off + o2 + i * 5120);
        }
      } while (bad2() && ++it < SPIN_MAX);
    }
#pragma unroll 1
    for (int ln = 0; ln < nl; ln++, offo += do2, po = 2048) {
      float d[4][4];
      uint32_t A[8];
#pragma unroll
      for (int h = 0; h < 2; h++) {
        mma16<false>(d[2 * h], cf[0][0].x, cf[0][0].y, cf[0][0].z, cf[0][0].w, v[h].x, v[2 + h].x);
        mma16<false>(d[2 * h + 1], cf[1][0].x, cf[1][0].y, cf[1][0].z, cf[1][0].w, v[h].y, v[2 + h].y);
      }
      if (ln) { fence_async_smem(); bar_arrive(15, NTHR); }
#pragma unroll
      for (int h = 0; h < 2; h++)
#pragma unroll
        for (int L = 0; L < 2; L++) {
          const uint4 tw = cf[L][2 + h];
          const float* z = d[2 * h + L];
          const float2 z0 = cmul(make_float2(z[0], z[2]), make_float2(__uint_as_float(tw.x), __uint_as_float(tw.y)));
          const float2 z1 = cmul(make_float2(z[1], z[3]), make_float2(__uint_as_float(tw.z), __uint_as_float(tw.w)));
          A[4 * h + L] = pack_bf16(z0.x, z0.y); A[4 * h + 2 + L] = pack_bf16(z1.x, z1.y);
        }
#pragma unroll
      for (int tt = 0; tt < 4; tt++) {
        mma16<false>(d[tt], A[0], A[1], A[2], A[3], G[tt].x, G[tt].y);
        mma16<true>(d[tt], A[4], A[5], A[6], A[7], G[tt].z, G[tt].w);
      }
#pragma unroll
      for (int tt = 0; tt < 4; tt++) {
        const float ar = d[tt][0], aj = d[tt][1], br = d[tt][2], bj = d[tt][3];
        const float2 y1 = cmul(make_float2(fmaf(-al, bj, ar), fmaf(al, br, aj)), make_float2(wc[4 * tt], wc[4 * tt + 1]));
        const float2 y2 = cmul(make_float2(fmaf(al, ar, bj), fmaf(al, aj, -br)), make_float2(wc[4 * tt + 2], wc[4 * tt + 3]));
        A[2 * tt] = pack_bf16(fmaf(al, y2.x, y1.x), fmaf(-al, y2.y, -y1.y));
        A[2 * tt + 1] = pack_bf16(fmaf(al, y1.y, -y2.y), fmaf(al, y1.x, -y2.x));
      }
#pragma unroll
      for (int i = 0; i < 16; i++) wc[i] = wn[i];
#pragma unroll
      for (int i = 0; i < 4; i++) v[i] = v2[i];
#pragma unroll
      for (int tt = 0; tt < 4; tt++) {
        mma16<false>(d[tt], A[0], A[1], A[2], A[3], G[tt].x, G[tt].y);
        mma16<true>(d[tt], A[4], A[5], A[6], A[7], G[tt].z, G[tt].w);
      }
#pragma unroll
      for (int h = 0; h < 2; h++)
#pragma unroll
        for (int L = 0; L < 2; L++) {
          const uint4 tw = cf[L][2 + h];
          const float2 z0 = cmul(make_float2(d[2 * h][2 * L], d[2 * h][2 * L + 1]), make_float2(__uint_as_float(tw.x), __uint_as_float(tw.y)));
          const float2 z1 = cmul(make_float2(d[2 * h + 1][2 * L], d[2 * h + 1][2 * L + 1]), make_float2(__uint_as_float(tw.z), __uint_as_float(tw.w)));
          A[4 * h + 2 * L] = movm(pack_bf16(z0.x, z1.x)); A[4 * h + 2 * L + 1] = movm(pack_bf16(z0.y, z1.y));
        }
#pragma unroll
      for (int h = 0; h < 2; h++) {
        mma16<false>(d[0], cf[0][1].x, cf[0][1].y, cf[0][1].z, cf[0][1].w, A[4 * h], A[4 * h + 1]);
        mma16<false>(d[1], cf[1][1].x, cf[1][1].y, cf[1][1].z, cf[1][1].w, A[4 * h + 2], A[4 * h + 3]);
#pragma unroll
        for (int e = 0; e < 2; e++)
          sts2(offo + (2 * h + e) * po, set_tag(pack_bf16(d[0][e], d[0][2 + e]), tagv), pack_bf16(d[1][e], d[1][2 + e]));
      }
      CK(12 + ln);
    }
    fence_async_smem();
    if (nl < 2 && wp != 8) bar_arrive(15, NTHR);
    if (wp & 7) { if (wg < 2) bar_arrive(6, 256); }
    else {
      if (wp) bar_sync(15, NTHR); else bar_sync(6, 256);
      if (elect()) {
        tma_st2d(mz2, sz2, cz2, 0);
        HW();
        if (wp == 0) { red_add(hz2, 1); TS(9); }
      }
      __syncwarp();
    }
  }
  if (wg == 2) {
#pragma unroll 1
    for (int u = 72 + cta, k = 0; u < 216; u += NCTA, k ^= 1) {
      if (R < 0) { fence_async_smem(); bar_sync(4, 128); load_wm(u); }
      mod_unit(sc, u, t128, sbase + O_NRM, full0 + 8 * B_WM, k, red + 256 - 256 * k, tag16);
    }
    fence_async_smem();
    CK(13);
  }

  const int grp = cta / 11, m1 = cta - 11 * grp;
  const bool helper = (m1 & 3) == 3;
  const int f1 = 384 * grp + (helper ? 192 : 128) * (m1 >> 2);
  const int d1 = 160 * (m1 & 3), flip = m1 >= 7;
  const int a1bytes = helper ? 24576 : 16384;
  auto load_a1 = [&](int st, int kb) {
    mbar_expect(full0 + 8 * st, a1bytes);
    tma4d_ef(sbase + st * STAGE, helper ? &maps.w1b : &maps.w1a, 4 * (kb >> 3), 16 * (kb & 7), f1 >> 6, full0 + 8 * st);
  };

  if (rows) {
#pragma unroll
    for (int kk = 0; kk < 4; kk++) af[kk] = __ldg(p.tab + TB_E + kk * 128 + t128);
    const uint4 c0 = lds4(sbase + O_ST + tid * 16), c1 = lds4(sbase + O_ST + 6144 + tid * 16);
    const uint2 c2 = lds2(sbase + O_ST + 12288 + tid * 8);
    const uint32_t tb[4] = {c0.x, c0.y, c0.z, c0.w}, sy[6] = {c1.x, c1.y, c1.z, c1.w, c2.x, c2.y};
    const uint32_t l8 = pin(8 * l), syl = pin(sbase + O_Y + wp * 2336 + 8 * l);
    const uint32_t sh3 = pin(sbase + O_B3 + (wp >> 1) * 4608 + (l >> 4) * 256 + (wp & 1) * 128 + ((((l >> 2) ^ (2 * cta + (wp & 1))) & 3) << 4) + (l & 3) * 4);
    const bool htag = (((sh3 >> 2) ^ (2 * cta + (wp & 1))) & 7) == 0;
    const uint32_t ham = pin(htag ? ~1u : ~0u), hom = pin(htag ? tag1 : 0u);
    const int slot = 4 * (cta >> 4) + ((cta >> 1) & 3) + 32 * (2 * ((cta >> 3) & 1) + (cta & 1));
    const uint32_t* zin = sc->z2 + (size_t)slot * 4800;
    if (wg == 2) {
      {
        uint4 v[4];
        const int i3 = min(t128 + 384, 431);
        int it = 0;
        while (true) {
          uint32_t bad = 0;
#pragma unroll
          for (int k = 0; k < 4; k++) v[k] = ld_rlx4(sc->mod + 4 * (k < 3 ? t128 + 128 * k : i3));
#pragma unroll
          for (int k = 0; k < 4; k++) {
            v[k].x ^= tag16; v[k].y ^= tag16; v[k].z ^= tag16; v[k].w ^= tag16;
            bad |= v[k].x | v[k].y | v[k].z | v[k].w;
          }
          if (!any(bad & 0xffffu) || ++it > SPIN_MAX) break;
        }
#pragma unroll
        for (int k = 0; k < 4; k++) sts4(sbase + O_MOD + 16 * (k < 3 ? t128 + 128 * k : i3), v[k].x, v[k].y, v[k].z, v[k].w);
      }
      CK(14);
      bar_sync(10, NTHR);
      mbar_wait(full0 + 8 * B_Z2, 0);
      if (elect()) {
        load_a1(wp - 8, wp - 8);
        if (wp > 8 && wp - 8 < NG1) prefetch_l2(reinterpret_cast<const uint8_t*>(p.w1) + (size_t)(128 * (4 * ((wp - 8) >> 1) + (cta >> 5)) + 64 * (wp & 1) + 2 * (cta & 31)) * (2 * F_), 4 * F_);
      }
      __syncwarp();
    } else {
      const uint4 e0 = lds4(sbase + O_ST + 15360 + tid * 16), e1 = lds4(sbase + O_ST + 19456 + tid * 16), e2 = lds4(sbase + O_ST + 23552 + tid * 16);
      const uint32_t lo[9] = {e0.x, e0.y, e0.z, e0.w, e1.x, e1.y, e1.z, e1.w, e2.x}, lx = e2.y, sb3 = e2.z;
      bar_arrive(10, NTHR);
      CK(14);
      if (wp == 1) {
        const uint32_t* zu = upin(zin);
        if (elect()) mbar_expect(full0 + 8 * B_Z2, 19200);
        wait_cnt(&sc->cnt[C_Z2], 120 * ep);
        if (elect()) {
          bulk_ld(sbase + O_IN, zu, 19200, full0 + 8 * B_Z2);
          TS(14);
        }
        __syncwarp();
      }
      mbar_wait(full0 + 8 * B_Z2, 0);
      CK(15);
      if (tid == 0) TS(11);
      uint2 v[10];
#pragma unroll
      for (int k1 = 0; k1 < 10; k1++) v[k1] = lds2(k1 < 9 ? lo[k1] : lx);
      auto bad3 = [&]() {
        return any(or3(or3(diff2(v[0].x, v[1].x, tag1), diff2(v[2].x, v[3].x, tag1), diff2(v[4].x, v[5].x, tag1)), diff2(v[6].x, v[7].x, tag1), diff2(v[8].x, v[9].x, tag1)) & 1);
      };
      if (__builtin_expect(bad3(), 0)) {
        FAILCNT(1);
        int it = 0;
        do {
#pragma unroll
          for (int k1 = 0; k1 < 10; k1++) v[k1] = ld_rlx2(reinterpret_cast<const uint8_t*>(zin) + ((k1 < 9 ? lo[k1] : lx) - (sbase + O_IN)));
        } while (bad3() && ++it < SPIN_MAX);
      }
      float2 za[9], zb[9];
#pragma unroll
      for (int i = 0; i < 9; i++) { za[i] = make_float2(bf_lo(v[i].x), bf_hi(v[i].x)); zb[i] = make_float2(bf_lo(v[i].y), bf_hi(v[i].y)); }
      if (kap == 0) {
#pragma unroll
        for (int k = 1; k < 5; k++) {
          float2 a = za[k], b = za[9 - k];
          za[k] = make_float2(a.x - b.y, a.y + b.x); za[9 - k] = make_float2(a.x + b.y, b.x - a.y);
          a = zb[k]; b = zb[9 - k];
          zb[k] = make_float2(a.x - b.y, a.y + b.x); zb[9 - k] = make_float2(a.x + b.y, b.x - a.y);
        }
        za[0].y = bf_lo(v[9].x); zb[0].y = bf_lo(v[9].y);
      }
      __syncwarp();
      dft9(za); dft9(zb);
#pragma unroll
      for (int n = 0; n < 8; n += 2) {
        const int i0 = (9 - n) % 9, i1 = 8 - n;
        stmatrix4(sb3 + n * 2048, pack_bf16(za[i0].x, zb[i0].x), pack_bf16(za[i0].y, zb[i0].y), pack_bf16(za[i1].x, zb[i1].x), pack_bf16(za[i1].y, zb[i1].y));
      }
      stmatrix2(sb3 + 8 * 2048, pack_bf16(za[1].x, zb[1].x), pack_bf16(za[1].y, zb[1].y));
      fence_async_smem();
    }
    CK(16);
    __syncthreads();
    CK(17);
    float acc[24];
    const uint32_t db = (((sbase + O_B3 + wg * 6144) & 0x3FFFF) >> 4) | ((128 >> 4) << 16);
    wg_fence();
#pragma unroll
    for (int kk = 0; kk < 4; kk++) wgmma_rs_48(acc, af[kk].x, af[kk].y, af[kk].z, af[kk].w, db + kk * 16, 1024 >> 4, kk);
    wg_commit();
    uint32_t ga[9];
    uint2 sh[9], sw[9];
    if (wg < 2) {
#pragma unroll
      for (int i = 0; i < 9; i++) {
        const uint2 v = lds2(l8 + sbase + O_MOD + 256 * i);
        ga[i] = __byte_perm(v.x, v.y, 0x7632);
        sh[i] = lds2(l8 + sbase + O_MOD + 4 * D_ + 256 * i);
        sw[i] = lds2(l8 + sbase + O_MOD + 8 * D_ + 256 * i);
      }
    }
    wg_wait<0>();
    reg_fence(acc);
    CK(18);
#pragma unroll
    for (int i = 0; i < 3; i++) {
      const float* a = &acc[8 * i];
      const uint32_t a0 = pack_bf16(a[0], a[1]), a1 = pack_bf16(a[2], a[3]), a2 = pack_bf16(a[4], a[5]), a3 = pack_bf16(a[6], a[7]);
#pragma unroll
      for (int jh = 0; jh < 2; jh++) {
        float y[4];
        mma16<false>(y, a0, a1, a2, a3, tb[2 * jh], tb[2 * jh + 1]);
        sts(sy[2 * i] + jh * (4 * 584 * 4), pack_bf16(y[0], y[1]));
        sts(sy[2 * i + 1] + jh * (4 * 584 * 4), pack_bf16(y[2], y[3]));
      }
    }
    CK(19);
    if (wg == 2) bar_arrive(7, NTHR);
    else {
      bar_sync(7, NTHR);
      CK(20);
      float a[18], b[18];
#pragma unroll
      for (int i = 0; i < 9; i++) {
        const uint2 y = lds2(syl + 256 * i);
        xr[i] = hfma2(ga[i], __byte_perm(y.x, y.y, 0x5410), xr[i]);
        xr[9 + i] = hfma2(ga[i], __byte_perm(y.x, y.y, 0x7632), xr[9 + i]);
        a[2 * i] = bf_lo(xr[i]); a[2 * i + 1] = bf_hi(xr[i]); b[2 * i] = bf_lo(xr[9 + i]); b[2 * i + 1] = bf_hi(xr[9 + i]);
      }
      float oa, ra, ob, rb;
      ln_stats2(a, b, 1.0f, oa, ra, ob, rb);
      CK(21);
#pragma unroll
      for (int i = 0; i < 9; i++) {
        const float c0 = __uint_as_float(sw[i].x), c1 = __uint_as_float(sw[i].y), s0 = __uint_as_float(sh[i].x), s1 = __uint_as_float(sh[i].y);
        a[2 * i] = fmaf(fmaf(a[2 * i], ra, oa), c0, s0); a[2 * i + 1] = fmaf(fmaf(a[2 * i + 1], ra, oa), c1, s1);
        b[2 * i] = fmaf(fmaf(b[2 * i], rb, ob), c0, s0); b[2 * i + 1] = fmaf(fmaf(b[2 * i + 1], rb, ob), c1, s1);
      }
      ln_stats2(a, b, 0.5f, oa, ra, ob, rb);
      CK(22);
#pragma unroll
      for (int i = 0; i < 9; i++) {
        sts(sh3 + i * 512, and_or(pack_bf16(fmaf(a[2 * i], ra, oa), fmaf(a[2 * i + 1], ra, oa)), ham, hom));
        sts(sh3 + i * 512 + 64, and_or(pack_bf16(fmaf(b[2 * i], rb, ob), fmaf(b[2 * i + 1], rb, ob)), ham, hom));
      }
      fence_async_smem();
      if (wp < 2 * H3G) bar_arrive(8, 32 + 64 * H3G); else bar_arrive(9, 288 - 64 * H3G);
      CK(23);
    }
  } else __syncthreads();

  const bool g2 = cta < 130 && (cta >> 1) != 56;
  const int z2 = cta < 112 ? cta : cta - 2, r = z2 >> 6;
  const int s2 = 128 * ((z2 >> 2) & 15), d2 = 144 * (z2 & 3);
  constexpr int XST = (33 + 36 - JSK - 1) % NST;
  constexpr int ST0 = (32 - JSK - 1) % NST, ST1 = 31 % NST;

  if (wg == 2) {
    asm volatile("setmaxnreg.dec.sync.aligned.u32 40;");
    auto load_b = [&](bool second, int i, int st) {
      const uint32_t lb = full0 + 8 * (B_LAND + st), bytes = second ? 18432 : STAGE - a1bytes;
      mbar_expect(lb, bytes);
      bulk_ld(sbase + (second ? st * STAGE2 + 16384 : st * STAGE + a1bytes),
              second ? sc->u + ((size_t)(36 * r + kb2_order(i)) * D_ + d2) * 128 : sc->h3 + ((size_t)(i * 18 + (d1 >> 5)) << 12), bytes, lb);
    };
    if (wp == 8) {
      int st = rows ? 4 : 0, ph = 1;
#pragma unroll 1
      for (int kb = st; kb < 32; kb++) {
        if (rows && (kb >> 1) == 2) mbar_wait(full0 + 8 * (B_S4 - 4 + kb), 0);
        mbar_wait(empty0 + 8 * st, ph);
        if (elect()) {
          load_a1(st, kb);
          if (kb >= PF2K && kb < PF2K + PF2 && g2)
            prefetch_l2(reinterpret_cast<const uint8_t*>(p.w2) + (size_t)(36 * r + kb2_order(kb - PF2K)) * 262144 + (z2 & 63) * 4096, 4096);
        }
        __syncwarp();
        ring_next<false>(st, ph);
      }
      if (g2) {
        st++;
#pragma unroll 1
        for (int i = 0; i < 36; i++) {
          if (i == HOLDA) mbar_wait(full0 + 8 * B_GO, 0);
          mbar_wait(empty0 + 8 * st, ph);
          if (elect()) {
            mbar_expect(full0 + 8 * st, 16384);
            tma3d_ef(sbase + st * STAGE2, &maps.w2, 64 * (36 * r + kb2_order(i)), s2 >> 6, full0 + 8 * st);
          }
          __syncwarp();
          ring_next<true>(st, ph);
        }
      }
    } else if (wp >= 10) {
      const int sw = wp - 10;
      if (rows) {
        const CUtensorMap* mp = upin(&maps.h3[sw]);
        const uint32_t src = upin(sbase + O_B3 + sw * (H3G * 4608)), c0 = upin(64 * (cta & 15)), c1 = upin(18 * (cta >> 4)), c2 = upin(H3G * sw);
        unsigned* flag = pin(&sc->cnt[C_H3 + (cta >> 4) + 8 * sw]);
        bar_sync(8 + sw, sw ? 288 - 64 * H3G : 32 + 64 * H3G);
        if (sw) mbar_wait(full0 + 8 * H3W, 0);
        if (elect()) {
          tma_st3d(mp, src, c0, c1, c2);
          mbar_arrive(full0 + 8 * B_S4);
          bulk_commit_wait();
          red_add(flag, 1);
          mbar_arrive(full0 + 8 * B_S5);
          TS(sw ? 24 : 13);
        }
        __syncwarp();
      }
      if (sw) {
        if (rows) {
          mbar_wait(full0 + 8 * B_S5, 0);
          if (elect()) { asm volatile("fence.acq_rel.gpu;" ::: "memory"); red_add(&sc->cnt[C_X + 64], 1); }
          __syncwarp();
        }
        if (g2) {
          uint2 v[3];
          int it = 0;
          do {
#pragma unroll
            for (int i = 0; i < 3; i++) v[i] = ld_rlx2(sc->mod + 3 * D_ + d2 + 2 * min(l + 32 * i, 71));
          } while (any(or3(diff2(v[0].x, v[0].y, tag16), diff2(v[1].x, v[1].y, tag16), diff2(v[2].x, v[2].y, tag16)) & 0xffffu) && ++it < SPIN_MAX);
#pragma unroll
          for (int i = 0; i < 3; i++) sts(sbase + O_GB + 4 * min(l + 32 * i, 71), __byte_perm(v[i].x, v[i].y, 0x7632));
          __syncwarp();
        }
        wait_cnt(&sc->cnt[C_X + 64], 128 * ep);
        if (elect()) mbar_arrive(full0 + 8 * B_X);
        __syncwarp();
      }
      uint32_t lph = 0;
      auto check_tiles = [&](bool second, int n, int st, uint32_t o1, uint32_t d2nd) {
        const uint32_t b1 = pin(sbase + o1), b2 = pin(sbase + o1 + d2nd);
        int i = 0, it = 0;
#pragma unroll 1
        do {
          const uint32_t so = st * (second ? STAGE2 : STAGE);
          mbar_wait(full0 + 8 * (B_LAND + st), (lph >> st) & 1);
          lph ^= 1u << st;
          uint32_t v[20];
#pragma unroll
          for (int k = 0; k < 20; k++) if (!second || k < 10 || k >= 12) v[k] = lds(k < 12 ? b1 + so + k * 1024 : b2 + so + (k - 12) * 1024); else v[k] = tag1;
#pragma unroll
          for (int k = 0; k < 10; k++) v[k] = diff2(v[2 * k], v[2 * k + 1], tag1);
          const uint32_t bad = or3(or3(or3(v[0], v[1], v[2]), or3(v[3], v[4], v[5]), v[6]), v[7], or3(v[8], v[9], 0));
          if (__builtin_expect(any(bad & 1) && ++it < SPIN_MAX, 0)) {
            FAILCNT(2 + second);
            fence_async_smem();
            __syncwarp();
            if (elect()) load_b(second, i, st);
            __syncwarp();
            continue;
          }
          if (elect()) mbar_arrive(full0 + 8 * st);
          if (++st == NST) st = 0;
          i++;
        } while (i < n);
      };
      if (!sw) check_tiles(false, NV1, 0, a1bytes + l * 32 + (l >> 2) * 4, helper ? 4096 : 12288);
      const bool first = helper || m1 < W0N;
#pragma unroll 1
      for (int k = sw ? first : !first; k <= sw; k++) {
        const uint32_t stg = sbase + (!k ? ST0 * STAGE : helper ? ST1 * STAGE : O_U1);
        const int kbA = (f1 >> 6) + (helper ? 2 : 1) * (k ^ flip), kbB = helper ? (f1 >> 6) + 1 : kbA;
        uint8_t* const uA = upin(sc->u + ((size_t)kbA * D_ + d1) * 128);
        uint8_t* const uB = upin(sc->u + ((size_t)kbB * D_ + (helper ? d1 : d1 + 96)) * 128);
        unsigned* const fA = pin(&sc->cnt[C_U + kbA]);
        unsigned* const fB = pin(&sc->cnt[C_U + kbB]);
        const bool slow = sw && !helper;
        bar_sync(11 + k, 160);
        if (!slow) { if (elect()) { bulk_st(uA, stg, 96 * 128); TS(k ? 31 : 30); } __syncwarp(); }
        bar_sync(13 + k, 160);
        if (slow) {
          if (g2) mbar_wait(full0 + 8 * B_GO, 0);
          if (first) pause(10 * TRK0);
#pragma unroll 1
          for (int i = 0; i < 20480; i += 2048) {
            if (elect()) bulk_st(uA + i, stg + i, 2048);
            pause(k ? TRKC : TRK0);
          }
        }
        if (elect()) {
          if (helper ? k : !slow) bulk_st(uB, stg + 96 * 128, helper ? 96 * 128 : 64 * 128);
          bulk_commit_wait();
          red_add(fA, 1);
          if (helper && k) red_add(fB, 1);
          if (!k || helper) mbar_arrive(empty0 + 8 * (k ? ST1 : ST0));
          TS(k ? 23 : 17);
          mbar_arrive(full0 + 8 * B_S5);
        }
        __syncwarp();
      }
      if (sw) {
        mbar_wait(full0 + 8 * B_S5, rows);
        if (elect()) { asm volatile("fence.acq_rel.gpu;" ::: "memory"); red_add(&sc->cnt[C_X], 1); }
        __syncwarp();
      }
      if (g2) {
        if (!sw) check_tiles(true, NV2, 3, 16384 + l * 32 + (4 * (g & 1) + (g >> 1)) * 4, 10240);
        else {
          wait_cnt(&sc->cnt[C_X], NCTA * ep);
          if (elect()) {
            mbar_arrive(full0 + 8 * B_X);
            if (cta == 0) sc->cnt[C_EP] = ep;
          }
          __syncwarp();
        }
        mbar_wait(full0 + 8 * B_X, 1);
        fence_async_glb();
        const CUtensorMap* mp = upin(&maps.out);
        const uint32_t c1 = upin(s2 + 64 * (sw ^ r));
#pragma unroll 1
        for (int i = 0; i < 3; i++) {
          const uint32_t src = upin(sbase + (sw ? XST * STAGE2 : O_U1) + i * 6144), c0 = upin(d2 + 48 * i);
          if (i == 0) bar_sync(OSPL < 8 && sw ? 4 : 2 + sw, 160);
          if (OSPL < 8 && sw && i == (OSPL + 1) / 3) bar_sync(3, 160);
          if (elect()) asm volatile("cp.reduce.async.bulk.tensor.2d.global.shared::cta.add.tile.bulk_group [%0, {%2, %3}], [%1];" ::"l"(mp), "r"(src), "r"(c0), "r"(c1) : "memory");
          __syncwarp();
        }
        if (elect()) { bulk_commit_wait_read(); TS(sw ? 22 : 1); }
      }
      __syncwarp();
    } else {
      uint64_t ready = 0;
      int st = 0, ph = 1;
#pragma unroll 1
      for (int kb = 0; kb < 32; kb++) {
        const uint8_t* src = upin(sc->h3 + ((size_t)(kb * 18 + (d1 >> 5)) << 12));
        const uint32_t dst = upin(sbase + st * STAGE + a1bytes), lb = full0 + 8 * ((kb < NV1 ? B_LAND : 0) + st);
        if (kb == NV1) { mbar_wait(full0 + 8 * B_X, 0); fence_async_glb(); ready = ~0ull; }
        if (rows && (kb >> 1) == 2) mbar_wait(full0 + 8 * (B_S4 - 4 + kb), 0);
        mbar_wait(empty0 + 8 * st, ph);
        if (elect()) mbar_expect(lb, STAGE - a1bytes);
        wait_flags(sc->cnt + C_H3, 32, (kb & 7) + (kb < 8 * H3G ? 0 : 8), 16 * ep, ready);
        if (elect()) bulk_ld(dst, src, STAGE - a1bytes, lb);
        ring_next<false>(st, ph);
      }
      if (g2) {
        ready = 0;
        st++;
#pragma unroll 1
        for (int i = 0; i < 36; i++) {
          const int kb = kb2_order(i);
          const uint8_t* src = upin(sc->u + ((size_t)(36 * r + kb) * D_ + d2) * 128);
          const uint32_t dst = upin(sbase + st * STAGE2 + 16384), lb = full0 + 8 * ((i < NV2 ? B_LAND : 0) + st);
          if (i == NV2) { mbar_wait(full0 + 8 * B_X, 1); fence_async_glb(); ready = ~0ull; }
          mbar_wait(empty0 + 8 * st, ph);
          if (elect()) mbar_expect(lb, 18432);
          wait_flags(sc->cnt + C_U + 36 * r, 36, kb, 4 * ep, ready);
          if (elect()) {
            bulk_ld(dst, src, 18432, lb);
            if (i == GOAT) mbar_arrive(full0 + 8 * B_GO);
          }
          ring_next<true>(st, ph);
        }
      }
    }
  } else {
    asm volatile("setmaxnreg.inc.sync.aligned.u32 232;");
    const int wgu = wg;
    constexpr uint32_t sb4 = sbase >> 4;
    const int w = wp & 3;
    Ring rg = {0, 0};
    uint32_t* const x1p = p.out + (size_t)(cta + 256 * wp) * 288 + l;
    const uint32_t ad = pin(sbase + (!wg ? ST0 * STAGE : helper ? ST1 * STAGE : O_U1) + (8 * (l >> 4) + (l & 7)) * 128 + (((2 * w + ((l >> 3) & 1)) ^ (l & 7)) << 4));
    const uint32_t uam = pin(g == 2 * t ? 0xfffefffeu : ~0u), uom = pin(g == 2 * t ? tag1 * 0x10001u : 0u);
    float acc[96];
    constexpr uint32_t LA = (8192 >> 4) << 16, LB = (4096 >> 4) << 16;
    {
      const int fa = f1 + (helper ? 128 : 64) * (wg ^ flip) + 16 * w + g, fb = helper ? f1 + 64 + 16 * w + g : fa;
      const float a0 = 0.5f * __bfloat162float(p.b1[fa]), a1 = 0.5f * __bfloat162float(p.b1[fa + 8]);
      const float b0 = 0.5f * __bfloat162float(p.b1[fb]), b1 = 0.5f * __bfloat162float(p.b1[fb + 8]);
#pragma unroll
      for (int i = 0; i < 96; i++) acc[i] = i < 48 ? ((i & 2) ? a1 : a0) : ((i & 2) ? b1 : b0);
      reg_fence(acc);
    }
    if (!helper) gemm_main<0>(acc, sb4 + (wgu ^ flip) * 512 + LA, 0, sb4 + 1024 + LB, wgu, rg, x1p, xr);
    else {
      float ac2[96];
#pragma unroll
      for (int i = 0; i < 96; i++) asm volatile("mov.b32 %0, %1;" : "=f"(ac2[i]) : "f"(acc[i]));
      gemm_main<1>(ac2, sb4 + (wgu ^ flip) * 1024 + LA, sb4 + 512 + LA, sb4 + 1536 + LB, wgu, rg, x1p, xr);
#pragma unroll
      for (int i = 0; i < 96; i++) asm volatile("mov.b32 %0, %1;" : "=f"(acc[i]) : "f"(ac2[i]));
    }
    if (t128 == 0) TS(wg ? 16 : 6);
    {
      float tp[2] = {0.f, 0.f};
#pragma unroll
      for (int j = 0; j < 12; j++) {
        const float* a = &acc[8 * j];
        const float k3 = j < 2 ? GK3 : fmaf(tp[j & 1], 0.0f, GK3);
        float o[8];
#pragma unroll
        for (int e = 0; e < 8; e++) {
          float z = a[e] * fmaf(a[e] * k3, a[e], GK1);
          asm("tanh.approx.f32 %0, %0;" : "+f"(z));
          if (e == GDEP) tp[j & 1] = z;
          o[e] = fmaf(a[e], z, a[e]);
        }
        stmatrix4t(ad + j * 2048, and_or(pack_bf16(o[0], o[1]), uam, uom), pack_bf16(o[2], o[3]), and_or(pack_bf16(o[4], o[5]), uam, uom), pack_bf16(o[6], o[7]));
        if (j == 5) {
          fence_async_smem();
          bar_arrive(11 + wgu, 160);
        }
        if ((j == 5 && helper && !wgu) || (j == 9 && !helper)) break;
      }
      fence_async_smem();
      bar_arrive(13 + wgu, 160);
      if (t128 == 0) TS(wg ? 29 : 28);
    }
    if (g2) {
      const int mb = wgu ^ r;
      uint32_t gb[18];
      {
        float a0 = 0.f, a1 = 0.f;
        if (wgu) { a0 = __bfloat162float(p.b2[s2 + 64 * mb + 16 * w + g]); a1 = __bfloat162float(p.b2[s2 + 64 * mb + 16 * w + 8 + g]); }
        const uint32_t t4 = pin(4 * t);
#pragma unroll
        for (int i = 0; i < 18; i++) gb[i] = lds(t4 + sbase + O_GB + 16 * i);
#pragma unroll
        for (int i = 0; i < 72; i++) acc[i] = (i & 2) ? a1 : a0;
      }
      const uint32_t xa = pin(sbase + (wg ? XST * STAGE2 : O_U1) + (16 * w + (l & 15)) * 96 + (l >> 4) * 16);
      rg.st++;
      gemm_main<3>(acc, sb4 + mb * 512 + LA, 0, sb4 + 1024 + (1 << 16), wgu, rg, x1p, xr);
      if (t128 == 0) TS(wg ? 20 : 19);
#pragma unroll
      for (int j = 0; j < 9; j++) {
        const float* a = &acc[8 * j];
        stmatrix4(xa + (j / 3) * 6144 + (j % 3) * 32, hmul2(gb[2 * j], pack_bf16(a[0], a[1])), hmul2(gb[2 * j], pack_bf16(a[2], a[3])),
                  hmul2(gb[2 * j + 1], pack_bf16(a[4], a[5])), hmul2(gb[2 * j + 1], pack_bf16(a[6], a[7])));
        if (j == 8 || (j == OSPL && wgu)) { fence_async_smem(); bar_arrive(2 + wgu + (j == 8 ? 0 : 1), 160); }
      }
      if (t128 == 0) TS(wg ? 7 : 21);
      __syncwarp();
    }
  }
}

typedef CUresult (*EncodeFn)(CUtensorMap*, CUtensorMapDataType, cuuint32_t, void*, const cuuint64_t*, const cuuint64_t*, const cuuint32_t*,
                             const cuuint32_t*, CUtensorMapInterleave, CUtensorMapSwizzle, CUtensorMapL2promotion, CUtensorMapFloatOOBfill);

struct Dim { cuuint64_t n, stride; cuuint32_t box; };
template <int RANK>
void make_map(EncodeFn enc, CUtensorMap* m, bool words, int swz, const void* ptr, const Dim (&d)[RANK]) {
  cuuint64_t gd[RANK], gs[RANK];
  cuuint32_t bx[RANK], es[RANK];
  for (int i = 0; i < RANK; i++) { gd[i] = d[i].n; gs[i] = d[i].stride; bx[i] = d[i].box; es[i] = 1; }
  enc(m, words ? CU_TENSOR_MAP_DATA_TYPE_UINT32 : CU_TENSOR_MAP_DATA_TYPE_BFLOAT16, RANK, const_cast<void*>(ptr), gd, gs + 1, bx, es,
      CU_TENSOR_MAP_INTERLEAVE_NONE, static_cast<CUtensorMapSwizzle>(swz),
      swz == 3 ? CU_TENSOR_MAP_L2_PROMOTION_L2_256B : CU_TENSOR_MAP_L2_PROMOTION_NONE, CU_TENSOR_MAP_FLOAT_OOB_FILL_NONE);
}

}

extern "C" void kernel_launch(void* const* d_in, const int* in_sizes, int n_in, void* d_out, int out_size) {
  (void)in_sizes; (void)n_in; (void)out_size;
  static EncodeFn enc = nullptr;
  static void *sptr = nullptr, *tptr = nullptr;
  if (!enc) {
    void* f = nullptr; cudaDriverEntryPointQueryResult qr;
    cudaGetDriverEntryPoint("cuTensorMapEncodeTiled", &f, cudaEnableDefault, &qr);
    enc = reinterpret_cast<EncodeFn>(f);
    cudaFuncSetAttribute(fused_kernel, cudaFuncAttributeMaxDynamicSharedMemorySize, SMEM_BYTES);
    cudaGetSymbolAddress(&sptr, g_s);
    cudaGetSymbolAddress(&tptr, T_TAB);
  }
  Params p;
  p.x = (const __nv_bfloat16*)d_in[0]; p.wr = (const __nv_bfloat16*)d_in[1]; p.wi = (const __nv_bfloat16*)d_in[2];
  p.b1 = (const __nv_bfloat16*)d_in[5]; p.b2 = (const __nv_bfloat16*)d_in[7];
  p.c = (const __nv_bfloat16*)d_in[8]; p.wmod = (const __nv_bfloat16*)d_in[9];
  p.w1 = (const __nv_bfloat16*)d_in[4]; p.w2 = (const __nv_bfloat16*)d_in[6];
  p.out = static_cast<uint32_t*>(d_out); p.s = static_cast<Scratch*>(sptr); p.tab = static_cast<const uint4*>(tptr);
  Maps maps;
  make_map<4>(enc, &maps.w1a, false, 3, p.w1, {{64, 0, 64}, {16, 128 * 2 * F_, 4}, {128, 2 * F_, 16}, {72, 128, 2}});
  make_map<4>(enc, &maps.w1b, false, 3, p.w1, {{64, 0, 64}, {16, 128 * 2 * F_, 4}, {128, 2 * F_, 16}, {72, 128, 3}});
  make_map<3>(enc, &maps.w2, false, 3, p.w2, {{64, 0, 64}, {F_, 2 * S_, 64}, {32, 128, 2}});
  make_map<2>(enc, &maps.out, false, 0, d_out, {{D_, 0, 48}, {S_, 2 * D_, 64}});
  make_map<2>(enc, &maps.z1, true, 0, p.s->z1, {{5120, 0, 40}, {120, 20480, 60}});
  for (int i = 0; i < 2; i++) make_map<2>(enc, &maps.z2[i], true, 0, p.s->z2, {{4800, 0, i ? 16u : 24u}, {128, 19200, 128}});
  for (int i = 0; i < 4; i++) make_map<2>(enc, &maps.wf[i], false, 2 - (i & 1), (i & 2) ? p.wi : p.wr, {{16 * DF_, 0, (i & 1) ? 16u : 32u}, {128, 32 * DF_, 128}});
  make_map<2>(enc, &maps.wm, false, 1, p.wmod, {{6 * D_, 0, 16}, {D_, 12 * D_, 192}});
  for (int i = 0; i < 2; i++) make_map<3>(enc, &maps.h3[i], true, 0, p.s->h3, {{1024, 0, 64}, {144, 4096, 18}, {4, 144 * 4096, i ? 4u - H3G : H3G}});
  fused_kernel<<<NCTA, NTHR, SMEM_BYTES, cudaStreamPerThread>>>(p, maps);
}
```

```cpp
#include <cuda_runtime.h>
#include <cuda_bf16.h>
#include <cuda.h>
#include <stdint.h>

namespace {

constexpr int S_ = 2048, D_ = 576, DF_ = 289, F_ = 4608;
constexpr int NCTA = 132, NTHR = 384;
constexpr int STAGE = 36864, NST = 6;
constexpr int STAGE2 = 34816, O_U1 = NST * STAGE2, O_GB = O_U1 + 20480, SMEM_BYTES = 232448;
constexpr uint32_t sbase = 1024, red = sbase + NST * STAGE, full0 = sbase + SMEM_BYTES - 256, empty0 = full0 + 8 * NST;
constexpr int O_NRM = 0, O_B1 = 19456, O_Z1 = 38912, O_P2 = 59392, O_ST = 3 * STAGE;
constexpr int O_RAW = 4 * STAGE;
constexpr int O_IN = 4 * STAGE, O_Y = O_IN + 19456, O_B3 = O_IN + 38912, O_MOD = O_IN + 57344;

__device__ __align__(128) const uint32_t T_TAB[5632] = {
0x3f803f80,0xbf803f80,0x3f803f80,0xbf803f80,0x3f803f80,0xbf803f80,0x3f803f80,0xbf803f80,0x3f803f80,0xbf803f80,0x3f803f80,0xbf803f80,
0x3f803f80,0xbf803f80,0x3f803f80,0xbf803f80,0x3f7f3f80,0xbdc90000,0x3f223f35,0xbf46bf35,0x3f753f7b,0xbe95be48,0x3ef13f0e,0xbf62bf55,
0x3f623f6d,0xbef1bec4,0x3e953ec4,0xbf75bf6d,0x3f463f55,0xbf22bf0e,0x3dc93e48,0xbf7fbf7b,0x3f7b3f80,0xbe480000,0xbe480000,0xbf7bbf80,
0x3f553f6d,0xbf0ebec4,0xbf0ebec4,0xbf55bf6d,0x3f0e3f35,0xbf55bf35,0xbf55bf35,0xbf0ebf35,0x3e483ec4,0xbf7bbf6d,0xbf7bbf6d,0xbe48bec4,
0x3f753f80,0xbe950000,0xbf62bf35,0xbef1bf35,0x3f223f55,0xbf46bf0e,0xbf7fbf7b,0x3dc9be48,0x3dc93ec4,0xbf7fbf6d,0xbf46bf6d,0x3f223ec4,
0xbef1be48,0xbf62bf7b,0xbe95bf0e,0x3f753f55,0x3f6d3f80,0xbec40000,0xbf6dbf80,0x3ec40000,0x3ec43f35,0xbf6dbf35,0xbec4bf35,0x3f6d3f35,
0xbec40000,0xbf6dbf80,0x3ec40000,0x3f6d3f80,0xbf6dbf35,0xbec4bf35,0x3f6d3f35,0x3ec43f35,0x3f623f80,0xbef10000,0xbe95bf35,0x3f753f35,
0x3dc93f0e,0xbf7fbf55,0x3f223e48,0x3f463f7b,0xbf46bec4,0xbf22bf6d,0x3f7f3f6d,0xbdc93ec4,0xbf75bf7b,0x3e95be48,0x3ef13f55,0xbf62bf0e,
0x3f553f80,0xbf0e0000,0x3f0e0000,0x3f553f80,0xbe483ec4,0xbf7bbf6d,0x3f7b3f6d,0xbe483ec4,0xbf7bbf35,0xbe48bf35,0x3e483f35,0xbf7bbf35,
0xbf0ebf6d,0x3f553ec4,0xbf55bec4,0xbf0ebf6d,0x3f463f80,0xbf220000,0x3f7f3f35,0x3dc93f35,0xbef13e48,0xbf62bf7b,0x3e953f55,0xbf75bf0e,
0xbf75bf6d,0x3e95bec4,0xbf62bec4,0xbef1bf6d,0x3dc9bf0e,0x3f7f3f55,0xbf22bf7b,0x3f463e48,0x3f353f80,0xbf350000,0x3f353f80,0xbf350000,
0xbf350000,0xbf35bf80,0xbf350000,0xbf35bf80,0xbf35bf80,0x3f350000,0xbf35bf80,0x3f350000,0x3f350000,0x3f353f80,0x3f350000,0x3f353f80,
0x3f223f80,0xbf460000,0xbdc93f35,0xbf7fbf35,0xbf62be48,0xbef1bf7b,0xbf75bf55,0x3e95bf0e,0xbe95bf6d,0x3f753ec4,0x3ef1bec4,0x3f623f6d,
0x3f7f3f0e,0x3dc93f55,0x3f463f7b,0xbf223e48,0x3f0e3f80,0xbf550000,0xbf550000,0xbf0ebf80,0xbf7bbec4,0xbe48bf6d,0xbe48bf6d,0x3f7b3ec4,
0x3e48bf35,0x3f7b3f35,0x3f7b3f35,0xbe483f35,0x3f553f6d,0xbf0e3ec4,0xbf0e3ec4,0xbf55bf6d,0x3ef13f80,0xbf620000,0xbf75bf35,0x3e95bf35,
0xbf7fbf0e,0x3dc9bf55,0x3f46be48,0x3f223f7b,0x3f22bec4,0x3f463f6d,0x3dc93f6d,0xbf7fbec4,0x3e953f7b,0xbf75be48,0xbf62bf55,0x3ef1bf0e,
0x3ec43f80,0xbf6d0000,0xbec4bf80,0x3f6d0000,0xbf6dbf35,0x3ec4bf35,0x3f6d3f35,0xbec43f35,0x3f6d0000,0x3ec43f80,0xbf6d0000,0xbec4bf80,
0xbec43f35,0xbf6dbf35,0x3ec4bf35,0x3f6d3f35,0x3e953f80,0xbf750000,0x3ef1bf35,0x3f623f35,0xbf46bf55,0x3f22bf0e,0x3dc93f7b,0xbf7fbe48,
0x3f7f3ec4,0xbdc93f6d,0xbf22bf6d,0x3f46bec4,0xbf623e48,0xbef1bf7b,0x3f753f0e,0xbe953f55,0x3e483f80,0xbf7b0000,0x3f7b0000,0x3e483f80,
0xbf0ebf6d,0x3f55bec4,0xbf553ec4,0xbf0ebf6d,0x3f553f35,0xbf0e3f35,0x3f0ebf35,0x3f553f35,0xbf7bbec4,0x3e48bf6d,0xbe483f6d,0xbf7bbec4,
0x3dc93f80,0xbf7f0000,0x3f463f35,0xbf223f35,0xbe95bf7b,0x3f75be48,0xbf62bf0e,0x3ef1bf55,0x3ef13f6d,0xbf623ec4,0x3f753ec4,0xbe953f6d,
0xbf22bf55,0x3f46bf0e,0xbf7fbe48,0x3dc9bf7b,0x3f80,0xbf800000,0x3f80,0xbf800000,0xbf80,0x3f800000,0xbf80,0x3f800000,
0x3f80,0xbf800000,0x3f80,0xbf800000,0xbf80,0x3f800000,0xbf80,0x3f800000,0xbdc93f80,0xbf7f0000,0xbf463f35,0xbf22bf35,
0x3e95bf7b,0x3f753e48,0x3f62bf0e,0x3ef13f55,0xbef13f6d,0xbf62bec4,0xbf753ec4,0xbe95bf6d,0x3f22bf55,0x3f463f0e,0x3f7fbe48,0x3dc93f7b,
0xbe483f80,0xbf7b0000,0xbf7b0000,0x3e48bf80,0x3f0ebf6d,0x3f553ec4,0x3f553ec4,0xbf0e3f6d,0xbf553f35,0xbf0ebf35,0xbf0ebf35,0x3f55bf35,
0x3f7bbec4,0x3e483f6d,0x3e483f6d,0xbf7b3ec4,0xbe953f80,0xbf750000,0xbef1bf35,0x3f62bf35,0x3f46bf55,0x3f223f0e,0xbdc93f7b,0xbf7f3e48,
0xbf7f3ec4,0xbdc9bf6d,0x3f22bf6d,0x3f463ec4,0x3f623e48,0xbef13f7b,0xbf753f0e,0xbe95bf55,0xbec43f80,0xbf6d0000,0x3ec4bf80,0x3f6d0000,
0x3f6dbf35,0x3ec43f35,0xbf6d3f35,0xbec4bf35,0xbf6d0000,0x3ec4bf80,0x3f6d0000,0xbec43f80,0x3ec43f35,0xbf6d3f35,0xbec4bf35,0x3f6dbf35,
0xbef13f80,0xbf620000,0x3f75bf35,0x3e953f35,0x3f7fbf0e,0x3dc93f55,0xbf46be48,0x3f22bf7b,0xbf22bec4,0x3f46bf6d,0xbdc93f6d,0xbf7f3ec4,
0xbe953f7b,0xbf753e48,0x3f62bf55,0x3ef13f0e,0xbf0e3f80,0xbf550000,0x3f550000,0xbf0e3f80,0x3f7bbec4,0xbe483f6d,0x3e48bf6d,0x3f7bbec4,
0xbe48bf35,0x3f7bbf35,0xbf7b3f35,0xbe48bf35,0xbf553f6d,0xbf0ebec4,0x3f0e3ec4,0xbf553f6d,0xbf223f80,0xbf460000,0x3dc93f35,0xbf7f3f35,
0x3f62be48,0xbef13f7b,0x3f75bf55,0x3e953f0e,0x3e95bf6d,0x3f75bec4,0xbef1bec4,0x3f62bf6d,0xbf7f3f0e,0x3dc9bf55,0xbf463f7b,0xbf22be48,
0xbf353f80,0xbf350000,0xbf353f80,0xbf350000,0x3f350000,0xbf353f80,0x3f350000,0xbf353f80,0x3f35bf80,0x3f350000,0x3f35bf80,0x3f350000,
0xbf350000,0x3f35bf80,0xbf350000,0x3f35bf80,0xbf463f80,0xbf220000,0xbf7f3f35,0x3dc9bf35,0x3ef13e48,0xbf623f7b,0xbe953f55,0xbf753f0e,
0x3f75bf6d,0x3e953ec4,0x3f62bec4,0xbef13f6d,0xbdc9bf0e,0x3f7fbf55,0x3f22bf7b,0x3f46be48,0xbf553f80,0xbf0e0000,0xbf0e0000,0x3f55bf80,
0x3e483ec4,0xbf7b3f6d,0xbf7b3f6d,0xbe48bec4,0x3f7bbf35,0xbe483f35,0xbe483f35,0xbf7b3f35,0x3f0ebf6d,0x3f55bec4,0x3f55bec4,0xbf0e3f6d,
0xbf623f80,0xbef10000,0x3e95bf35,0x3f75bf35,0xbdc93f0e,0xbf7f3f55,0xbf223e48,0x3f46bf7b,0x3f46bec4,0xbf223f6d,0xbf7f3f6d,0xbdc9bec4,
0x3f75bf7b,0x3e953e48,0xbef13f55,0xbf623f0e,0xbf6d3f80,0xbec40000,0x3f6dbf80,0x3ec40000,0xbec43f35,0xbf6d3f35,0x3ec4bf35,0x3f6dbf35,
0x3ec40000,0xbf6d3f80,0xbec40000,0x3f6dbf80,0x3f6dbf35,0xbec43f35,0xbf6d3f35,0x3ec4bf35,0xbf753f80,0xbe950000,0x3f62bf35,0xbef13f35,
0xbf223f55,0xbf463f0e,0x3f7fbf7b,0x3dc93e48,0xbdc93ec4,0xbf7f3f6d,0x3f46bf6d,0x3f22bec4,0x3ef1be48,0xbf623f7b,0x3e95bf0e,0x3f75bf55,
0xbf7b3f80,0xbe480000,0x3e480000,0xbf7b3f80,0xbf553f6d,0xbf0e3ec4,0x3f0ebec4,0xbf553f6d,0xbf0e3f35,0xbf553f35,0x3f55bf35,0xbf0e3f35,
0xbe483ec4,0xbf7b3f6d,0x3f7bbf6d,0xbe483ec4,0xbf7f3f80,0xbdc90000,0xbf223f35,0xbf463f35,0xbf753f7b,0xbe953e48,0xbef13f0e,0xbf623f55,
0xbf623f6d,0xbef13ec4,0xbe953ec4,0xbf753f6d,0xbf463f55,0xbf223f0e,0xbdc93e48,0xbf7f3f7b,0x3f803f80,0xbf803f80,0x3f803f80,0xbf803f80,
0x3f803f80,0xbf803f80,0x3f803f80,0xbf803f80,0x3f803f80,0xbf803f80,0x3f803f80,0xbf803f80,0x3f803f80,0xbf803f80,0x3f803f80,0xbf803f80,
0xbdc90000,0xbf7fbf80,0xbf46bf35,0xbf22bf35,0xbe95be48,0xbf75bf7b,0xbf62bf55,0xbef1bf0e,0xbef1bec4,0xbf62bf6d,0xbf75bf6d,0xbe95bec4,
0xbf22bf0e,0xbf46bf55,0xbf7fbf7b,0xbdc9be48,0xbf7bbf80,0x3e480000,0x3e480000,0x3f7b3f80,0xbf55bf6d,0x3f0e3ec4,0x3f0e3ec4,0x3f553f6d,
0xbf0ebf35,0x3f553f35,0x3f553f35,0x3f0e3f35,0xbe48bec4,0x3f7b3f6d,0x3f7b3f6d,0x3e483ec4,0x3e950000,0x3f753f80,0x3ef13f35,0xbf62bf35,
0x3f463f0e,0x3f223f55,0xbdc93e48,0xbf7fbf7b,0x3f7f3f6d,0x3dc93ec4,0xbf22bec4,0xbf46bf6d,0x3f623f7b,0xbef1be48,0xbf75bf55,0xbe95bf0e,
0x3f6d3f80,0xbec40000,0xbf6dbf80,0x3ec40000,0x3ec43f35,0xbf6dbf35,0xbec4bf35,0x3f6d3f35,0xbec40000,0xbf6dbf80,0x3ec40000,0x3f6d3f80,
0xbf6dbf35,0xbec4bf35,0x3f6d3f35,0x3ec43f35,0xbef10000,0xbf62bf80,0x3f753f35,0x3e953f35,0xbf7fbf55,0xbdc9bf0e,0x3f463f7b,0xbf22be48,
0xbf22bf6d,0x3f463ec4,0xbdc93ec4,0xbf7fbf6d,0x3e95be48,0x3f753f7b,0xbf62bf0e,0xbef1bf55,0xbf55bf80,0x3f0e0000,0xbf0e0000,0xbf55bf80,
0x3e48bec4,0x3f7b3f6d,0xbf7bbf6d,0x3e48bec4,0x3f7b3f35,0x3e483f35,0xbe48bf35,0x3f7b3f35,0x3f0e3f6d,0xbf55bec4,0x3f553ec4,0x3f0e3f6d,
0x3f220000,0x3f463f80,0xbdc9bf35,0x3f7f3f35,0x3f623f7b,0xbef13e48,0x3f753f0e,0x3e953f55,0xbe953ec4,0xbf75bf6d,0x3ef13f6d,0xbf62bec4,
0xbf7fbf55,0x3dc9bf0e,0xbf46be48,0xbf22bf7b,0x3f353f80,0xbf350000,0x3f353f80,0xbf350000,0xbf350000,0xbf35bf80,0xbf350000,0xbf35bf80,
0xbf35bf80,0x3f350000,0xbf35bf80,0x3f350000,0x3f350000,0x3f353f80,0x3f350000,0x3f353f80,0xbf460000,0xbf22bf80,0xbf7fbf35,0x3dc9bf35,
0xbef1bf7b,0x3f623e48,0x3e95bf0e,0x3f753f55,0x3f753ec4,0x3e953f6d,0x3f623f6d,0xbef13ec4,0x3dc93f55,0xbf7fbf0e,0xbf223e48,0xbf46bf7b,
0xbf0ebf80,0x3f550000,0x3f550000,0x3f0e3f80,0x3f7b3ec4,0x3e483f6d,0x3e483f6d,0xbf7bbec4,0xbe483f35,0xbf7bbf35,0xbf7bbf35,0x3e48bf35,
0xbf55bf6d,0x3f0ebec4,0x3f0ebec4,0x3f553f6d,0x3f620000,0x3ef13f80,0xbe953f35,0xbf75bf35,0xbdc93f55,0xbf7fbf0e,0xbf22bf7b,0x3f46be48,
0xbf46bf6d,0x3f22bec4,0x3f7f3ec4,0x3dc93f6d,0x3f753e48,0x3e953f7b,0xbef13f0e,0xbf62bf55,0x3ec43f80,0xbf6d0000,0xbec4bf80,0x3f6d0000,
0xbf6dbf35,0x3ec4bf35,0x3f6d3f35,0xbec43f35,0x3f6d0000,0x3ec43f80,0xbf6d0000,0xbec4bf80,0xbec43f35,0xbf6dbf35,0x3ec4bf35,0x3f6d3f35,
0xbf750000,0xbe95bf80,0x3f623f35,0xbef13f35,0x3f22bf0e,0x3f463f55,0xbf7fbe48,0xbdc9bf7b,0xbdc93f6d,0xbf7fbec4,0x3f46bec4,0x3f223f6d,
0xbef1bf7b,0x3f62be48,0xbe953f55,0xbf75bf0e,0xbe48bf80,0x3f7b0000,0xbf7b0000,0xbe48bf80,0x3f0e3f6d,0xbf553ec4,0x3f55bec4,0x3f0e3f6d,
0xbf55bf35,0x3f0ebf35,0xbf0e3f35,0xbf55bf35,0x3f7b3ec4,0xbe483f6d,0x3e48bf6d,0x3f7b3ec4,0x3f7f0000,0x3dc93f80,0x3f22bf35,0x3f463f35,
0xbf753e48,0xbe95bf7b,0xbef13f55,0xbf62bf0e,0x3f62bec4,0x3ef13f6d,0x3e95bf6d,0x3f753ec4,0xbf463f0e,0xbf22bf55,0xbdc93f7b,0xbf7fbe48,
0x3f80,0xbf800000,0x3f80,0xbf800000,0xbf80,0x3f800000,0xbf80,0x3f800000,0x3f80,0xbf800000,0x3f80,0xbf800000,
0xbf80,0x3f800000,0xbf80,0x3f800000,0xbf7f0000,0x3dc9bf80,0xbf22bf35,0x3f46bf35,0x3f753e48,0xbe953f7b,0x3ef13f55,0xbf623f0e,
0xbf62bec4,0x3ef1bf6d,0xbe95bf6d,0x3f75bec4,0x3f463f0e,0xbf223f55,0x3dc93f7b,0xbf7f3e48,0x3e48bf80,0x3f7b0000,0x3f7b0000,0xbe483f80,
0xbf0e3f6d,0xbf55bec4,0xbf55bec4,0x3f0ebf6d,0x3f55bf35,0x3f0e3f35,0x3f0e3f35,0xbf553f35,0xbf7b3ec4,0xbe48bf6d,0xbe48bf6d,0x3f7bbec4,
0x3f750000,0xbe953f80,0xbf623f35,0xbef1bf35,0xbf22bf0e,0x3f46bf55,0x3f7fbe48,0xbdc93f7b,0x3dc93f6d,0xbf7f3ec4,0xbf46bec4,0x3f22bf6d,
0x3ef1bf7b,0x3f623e48,0x3e953f55,0xbf753f0e,0xbec43f80,0xbf6d0000,0x3ec4bf80,0x3f6d0000,0x3f6dbf35,0x3ec43f35,0xbf6d3f35,0xbec4bf35,
0xbf6d0000,0x3ec4bf80,0x3f6d0000,0xbec43f80,0x3ec43f35,0xbf6d3f35,0xbec4bf35,0x3f6dbf35,0xbf620000,0x3ef1bf80,0x3e953f35,0xbf753f35,
0x3dc93f55,0xbf7f3f0e,0x3f22bf7b,0x3f463e48,0x3f46bf6d,0x3f223ec4,0xbf7f3ec4,0x3dc9bf6d,0xbf753e48,0x3e95bf7b,0x3ef13f0e,0xbf623f55,
0x3f0ebf80,0x3f550000,0xbf550000,0x3f0ebf80,0xbf7b3ec4,0x3e48bf6d,0xbe483f6d,0xbf7b3ec4,0x3e483f35,0xbf7b3f35,0x3f7bbf35,0x3e483f35,
0x3f55bf6d,0x3f0e3ec4,0xbf0ebec4,0x3f55bf6d,0x3f460000,0xbf223f80,0x3f7fbf35,0x3dc93f35,0x3ef1bf7b,0x3f62be48,0xbe95bf0e,0x3f75bf55,
0xbf753ec4,0x3e95bf6d,0xbf623f6d,0xbef1bec4,0xbdc93f55,0xbf7f3f0e,0x3f223e48,0xbf463f7b,0xbf353f80,0xbf350000,0xbf353f80,0xbf350000,
0x3f350000,0xbf353f80,0x3f350000,0xbf353f80,0x3f35bf80,0x3f350000,0x3f35bf80,0x3f350000,0xbf350000,0x3f35bf80,0xbf350000,0x3f35bf80,
0xbf220000,0x3f46bf80,0x3dc9bf35,0x3f7fbf35,0xbf623f7b,0xbef1be48,0xbf753f0e,0x3e95bf55,0x3e953ec4,0xbf753f6d,0xbef13f6d,0xbf623ec4,
0x3f7fbf55,0x3dc93f0e,0x3f46be48,0xbf223f7b,0x3f55bf80,0x3f0e0000,0x3f0e0000,0xbf553f80,0xbe48bec4,0x3f7bbf6d,0x3f7bbf6d,0x3e483ec4,
0xbf7b3f35,0x3e48bf35,0x3e48bf35,0x3f7bbf35,0xbf0e3f6d,0xbf553ec4,0xbf553ec4,0x3f0ebf6d,0x3ef10000,0xbf623f80,0xbf753f35,0x3e95bf35,
0x3f7fbf55,0xbdc93f0e,0xbf463f7b,0xbf223e48,0x3f22bf6d,0x3f46bec4,0x3dc93ec4,0xbf7f3f6d,0xbe95be48,0x3f75bf7b,0x3f62bf0e,0xbef13f55,
0xbf6d3f80,0xbec40000,0x3f6dbf80,0x3ec40000,0xbec43f35,0xbf6d3f35,0x3ec4bf35,0x3f6dbf35,0x3ec40000,0xbf6d3f80,0xbec40000,0x3f6dbf80,
0x3f6dbf35,0xbec43f35,0xbf6d3f35,0x3ec4bf35,0xbe950000,0x3f75bf80,0xbef13f35,0xbf623f35,0xbf463f0e,0x3f22bf55,0x3dc93e48,0xbf7f3f7b,
0xbf7f3f6d,0x3dc9bec4,0x3f22bec4,0xbf463f6d,0xbf623f7b,0xbef13e48,0x3f75bf55,0xbe953f0e,0x3f7bbf80,0x3e480000,0xbe480000,0x3f7bbf80,
0x3f55bf6d,0x3f0ebec4,0xbf0e3ec4,0x3f55bf6d,0x3f0ebf35,0x3f55bf35,0xbf553f35,0x3f0ebf35,0x3e48bec4,0x3f7bbf6d,0xbf7b3f6d,0x3e48bec4,
0x3dc90000,0xbf7f3f80,0x3f46bf35,0xbf223f35,0x3e95be48,0xbf753f7b,0x3f62bf55,0xbef13f0e,0x3ef1bec4,0xbf623f6d,0x3f75bf6d,0xbe953ec4,
0x3f22bf0e,0xbf463f55,0x3f7fbf7b,0xbdc93e48,0x3f803f80,0xbf803f80,0x3f803f80,0xbf803f80,0x3f803f80,0xbf803f80,0x3f803f80,0xbf803f80,
0x3f803f80,0xbf803f80,0x3f803f80,0xbf803f80,0x3f803f80,0xbf803f80,0x3f803f80,0xbf803f80,0xbf7fbf80,0x3dc90000,0xbf22bf35,0x3f463f35,
0xbf75bf7b,0x3e953e48,0xbef1bf0e,0x3f623f55,0xbf62bf6d,0x3ef13ec4,0xbe95bec4,0x3f753f6d,0xbf46bf55,0x3f223f0e,0xbdc9be48,0x3f7f3f7b,
0x3f7b3f80,0xbe480000,0xbe480000,0xbf7bbf80,0x3f553f6d,0xbf0ebec4,0xbf0ebec4,0xbf55bf6d,0x3f0e3f35,0xbf55bf35,0xbf55bf35,0xbf0ebf35,
0x3e483ec4,0xbf7bbf6d,0xbf7bbf6d,0xbe48bec4,0xbf75bf80,0x3e950000,0x3f623f35,0x3ef13f35,0xbf22bf55,0x3f463f0e,0x3f7f3f7b,0xbdc93e48,
0xbdc9bec4,0x3f7f3f6d,0x3f463f6d,0xbf22bec4,0x3ef13e48,0x3f623f7b,0x3e953f0e,0xbf75bf55,0x3f6d3f80,0xbec40000,0xbf6dbf80,0x3ec40000,
0x3ec43f35,0xbf6dbf35,0xbec4bf35,0x3f6d3f35,0xbec40000,0xbf6dbf80,0x3ec40000,0x3f6d3f80,0xbf6dbf35,0xbec4bf35,0x3f6d3f35,0x3ec43f35,
0xbf62bf80,0x3ef10000,0x3e953f35,0xbf75bf35,0xbdc9bf0e,0x3f7f3f55,0xbf22be48,0xbf46bf7b,0x3f463ec4,0x3f223f6d,0xbf7fbf6d,0x3dc9bec4,
0x3f753f7b,0xbe953e48,0xbef1bf55,0x3f623f0e,0x3f553f80,0xbf0e0000,0x3f0e0000,0x3f553f80,0xbe483ec4,0xbf7bbf6d,0x3f7b3f6d,0xbe483ec4,
0xbf7bbf35,0xbe48bf35,0x3e483f35,0xbf7bbf35,0xbf0ebf6d,0x3f553ec4,0xbf55bec4,0xbf0ebf6d,0xbf46bf80,0x3f220000,0xbf7fbf35,0xbdc9bf35,
0x3ef1be48,0x3f623f7b,0xbe95bf55,0x3f753f0e,0x3f753f6d,0xbe953ec4,0x3f623ec4,0x3ef13f6d,0xbdc93f0e,0xbf7fbf55,0x3f223f7b,0xbf46be48,
0x3f353f80,0xbf350000,0x3f353f80,0xbf350000,0xbf350000,0xbf35bf80,0xbf350000,0xbf35bf80,0xbf35bf80,0x3f350000,0xbf35bf80,0x3f350000,
0x3f350000,0x3f353f80,0x3f350000,0x3f353f80,0xbf22bf80,0x3f460000,0x3dc9bf35,0x3f7f3f35,0x3f623e48,0x3ef13f7b,0x3f753f55,0xbe953f0e,
0x3e953f6d,0xbf75bec4,0xbef13ec4,0xbf62bf6d,0xbf7fbf0e,0xbdc9bf55,0xbf46bf7b,0x3f22be48,0x3f0e3f80,0xbf550000,0xbf550000,0xbf0ebf80,
0xbf7bbec4,0xbe48bf6d,0xbe48bf6d,0x3f7b3ec4,0x3e48bf35,0x3f7b3f35,0x3f7b3f35,0xbe483f35,0x3f553f6d,0xbf0e3ec4,0xbf0e3ec4,0xbf55bf6d,
0xbef1bf80,0x3f620000,0x3f753f35,0xbe953f35,0x3f7f3f0e,0xbdc93f55,0xbf463e48,0xbf22bf7b,0xbf223ec4,0xbf46bf6d,0xbdc9bf6d,0x3f7f3ec4,
0xbe95bf7b,0x3f753e48,0x3f623f55,0xbef13f0e,0x3ec43f80,0xbf6d0000,0xbec4bf80,0x3f6d0000,0xbf6dbf35,0x3ec4bf35,0x3f6d3f35,0xbec43f35,
0x3f6d0000,0x3ec43f80,0xbf6d0000,0xbec4bf80,0xbec43f35,0xbf6dbf35,0x3ec4bf35,0x3f6d3f35,0xbe95bf80,0x3f750000,0xbef13f35,0xbf62bf35,
0x3f463f55,0xbf223f0e,0xbdc9bf7b,0x3f7f3e48,0xbf7fbec4,0x3dc9bf6d,0x3f223f6d,0xbf463ec4,0x3f62be48,0x3ef13f7b,0xbf75bf0e,0x3e95bf55,
0x3e483f80,0xbf7b0000,0x3f7b0000,0x3e483f80,0xbf0ebf6d,0x3f55bec4,0xbf553ec4,0xbf0ebf6d,0x3f553f35,0xbf0e3f35,0x3f0ebf35,0x3f553f35,
0xbf7bbec4,0x3e48bf6d,0xbe483f6d,0xbf7bbec4,0xbdc9bf80,0x3f7f0000,0xbf46bf35,0x3f22bf35,0x3e953f7b,0xbf753e48,0x3f623f0e,0xbef13f55,
0xbef1bf6d,0x3f62bec4,0xbf75bec4,0x3e95bf6d,0x3f223f55,0xbf463f0e,0x3f7f3e48,0xbdc93f7b,0x3f80,0xbf800000,0x3f80,0xbf800000,
0xbf80,0x3f800000,0xbf80,0x3f800000,0x3f80,0xbf800000,0x3f80,0xbf800000,0xbf80,0x3f800000,0xbf80,0x3f800000,
0x3dc9bf80,0x3f7f0000,0x3f46bf35,0x3f223f35,0xbe953f7b,0xbf75be48,0xbf623f0e,0xbef1bf55,0x3ef1bf6d,0x3f623ec4,0x3f75bec4,0x3e953f6d,
0xbf223f55,0xbf46bf0e,0xbf7f3e48,0xbdc9bf7b,0xbe483f80,0xbf7b0000,0xbf7b0000,0x3e48bf80,0x3f0ebf6d,0x3f553ec4,0x3f553ec4,0xbf0e3f6d,
0xbf553f35,0xbf0ebf35,0xbf0ebf35,0x3f55bf35,0x3f7bbec4,0x3e483f6d,0x3e483f6d,0xbf7b3ec4,0x3e95bf80,0x3f750000,0x3ef13f35,0xbf623f35,
0xbf463f55,0xbf22bf0e,0x3dc9bf7b,0x3f7fbe48,0x3f7fbec4,0x3dc93f6d,0xbf223f6d,0xbf46bec4,0xbf62be48,0x3ef1bf7b,0x3f75bf0e,0x3e953f55,
0xbec43f80,0xbf6d0000,0x3ec4bf80,0x3f6d0000,0x3f6dbf35,0x3ec43f35,0xbf6d3f35,0xbec4bf35,0xbf6d0000,0x3ec4bf80,0x3f6d0000,0xbec43f80,
0x3ec43f35,0xbf6d3f35,0xbec4bf35,0x3f6dbf35,0x3ef1bf80,0x3f620000,0xbf753f35,0xbe95bf35,0xbf7f3f0e,0xbdc9bf55,0x3f463e48,0xbf223f7b,
0x3f223ec4,0xbf463f6d,0x3dc9bf6d,0x3f7fbec4,0x3e95bf7b,0x3f75be48,0xbf623f55,0xbef1bf0e,0xbf0e3f80,0xbf550000,0x3f550000,0xbf0e3f80,
0x3f7bbec4,0xbe483f6d,0x3e48bf6d,0x3f7bbec4,0xbe48bf35,0x3f7bbf35,0xbf7b3f35,0xbe48bf35,0xbf553f6d,0xbf0ebec4,0x3f0e3ec4,0xbf553f6d,
0x3f22bf80,0x3f460000,0xbdc9bf35,0x3f7fbf35,0xbf623e48,0x3ef1bf7b,0xbf753f55,0xbe95bf0e,0xbe953f6d,0xbf753ec4,0x3ef13ec4,0xbf623f6d,
0x3f7fbf0e,0xbdc93f55,0x3f46bf7b,0x3f223e48,0xbf353f80,0xbf350000,0xbf353f80,0xbf350000,0x3f350000,0xbf353f80,0x3f350000,0xbf353f80,
0x3f35bf80,0x3f350000,0x3f35bf80,0x3f350000,0xbf350000,0x3f35bf80,0xbf350000,0x3f35bf80,0x3f46bf80,0x3f220000,0x3f7fbf35,0xbdc93f35,
0xbef1be48,0x3f62bf7b,0x3e95bf55,0x3f75bf0e,0xbf753f6d,0xbe95bec4,0xbf623ec4,0x3ef1bf6d,0x3dc93f0e,0xbf7f3f55,0xbf223f7b,0xbf463e48,
0xbf553f80,0xbf0e0000,0xbf0e0000,0x3f55bf80,0x3e483ec4,0xbf7b3f6d,0xbf7b3f6d,0xbe48bec4,0x3f7bbf35,0xbe483f35,0xbe483f35,0xbf7b3f35,
0x3f0ebf6d,0x3f55bec4,0x3f55bec4,0xbf0e3f6d,0x3f62bf80,0x3ef10000,0xbe953f35,0xbf753f35,0x3dc9bf0e,0x3f7fbf55,0x3f22be48,0xbf463f7b,
0xbf463ec4,0x3f22bf6d,0x3f7fbf6d,0x3dc93ec4,0xbf753f7b,0xbe95be48,0x3ef1bf55,0x3f62bf0e,0xbf6d3f80,0xbec40000,0x3f6dbf80,0x3ec40000,
0xbec43f35,0xbf6d3f35,0x3ec4bf35,0x3f6dbf35,0x3ec40000,0xbf6d3f80,0xbec40000,0x3f6dbf80,0x3f6dbf35,0xbec43f35,0xbf6d3f35,0x3ec4bf35,
0x3f75bf80,0x3e950000,0xbf623f35,0x3ef1bf35,0x3f22bf55,0x3f46bf0e,0xbf7f3f7b,0xbdc9be48,0x3dc9bec4,0x3f7fbf6d,0xbf463f6d,0xbf223ec4,
0xbef13e48,0x3f62bf7b,0xbe953f0e,0xbf753f55,0xbf7b3f80,0xbe480000,0x3e480000,0xbf7b3f80,0xbf553f6d,0xbf0e3ec4,0x3f0ebec4,0xbf553f6d,
0xbf0e3f35,0xbf553f35,0x3f55bf35,0xbf0e3f35,0xbe483ec4,0xbf7b3f6d,0x3f7bbf6d,0xbe483ec4,0x3f7fbf80,0x3dc90000,0x3f22bf35,0x3f46bf35,
0x3f75bf7b,0x3e95be48,0x3ef1bf0e,0x3f62bf55,0x3f62bf6d,0x3ef1bec4,0x3e95bec4,0x3f75bf6d,0x3f46bf55,0x3f22bf0e,0x3dc9be48,0x3f7fbf7b,
0x3f803f80,0xbf803f80,0x3f803f80,0xbf803f80,0x3f803f80,0xbf803f80,0x3f803f80,0xbf803f80,0x3f803f80,0xbf803f80,0x3f803f80,0xbf803f80,
0x3f803f80,0xbf803f80,0x3f803f80,0xbf803f80,0x3dc90000,0x3f7f3f80,0x3f463f35,0x3f223f35,0x3e953e48,0x3f753f7b,0x3f623f55,0x3ef13f0e,
0x3ef13ec4,0x3f623f6d,0x3f753f6d,0x3e953ec4,0x3f223f0e,0x3f463f55,0x3f7f3f7b,0x3dc93e48,0xbf7bbf80,0x3e480000,0x3e480000,0x3f7b3f80,
0xbf55bf6d,0x3f0e3ec4,0x3f0e3ec4,0x3f553f6d,0xbf0ebf35,0x3f553f35,0x3f553f35,0x3f0e3f35,0xbe48bec4,0x3f7b3f6d,0x3f7b3f6d,0x3e483ec4,
0xbe950000,0xbf75bf80,0xbef1bf35,0x3f623f35,0xbf46bf0e,0xbf22bf55,0x3dc9be48,0x3f7f3f7b,0xbf7fbf6d,0xbdc9bec4,0x3f223ec4,0x3f463f6d,
0xbf62bf7b,0x3ef13e48,0x3f753f55,0x3e953f0e,0x3f6d3f80,0xbec40000,0xbf6dbf80,0x3ec40000,0x3ec43f35,0xbf6dbf35,0xbec4bf35,0x3f6d3f35,
0xbec40000,0xbf6dbf80,0x3ec40000,0x3f6d3f80,0xbf6dbf35,0xbec4bf35,0x3f6d3f35,0x3ec43f35,0x3ef10000,0x3f623f80,0xbf75bf35,0xbe95bf35,
0x3f7f3f55,0x3dc93f0e,0xbf46bf7b,0x3f223e48,0x3f223f6d,0xbf46bec4,0x3dc9bec4,0x3f7f3f6d,0xbe953e48,0xbf75bf7b,0x3f623f0e,0x3ef13f55,
0xbf55bf80,0x3f0e0000,0xbf0e0000,0xbf55bf80,0x3e48bec4,0x3f7b3f6d,0xbf7bbf6d,0x3e48bec4,0x3f7b3f35,0x3e483f35,0xbe48bf35,0x3f7b3f35,
0x3f0e3f6d,0xbf55bec4,0x3f553ec4,0x3f0e3f6d,0xbf220000,0xbf46bf80,0x3dc93f35,0xbf7fbf35,0xbf62bf7b,0x3ef1be48,0xbf75bf0e,0xbe95bf55,
0x3e95bec4,0x3f753f6d,0xbef1bf6d,0x3f623ec4,0x3f7f3f55,0xbdc93f0e,0x3f463e48,0x3f223f7b,0x3f353f80,0xbf350000,0x3f353f80,0xbf350000,
0xbf350000,0xbf35bf80,0xbf350000,0xbf35bf80,0xbf35bf80,0x3f350000,0xbf35bf80,0x3f350000,0x3f350000,0x3f353f80,0x3f350000,0x3f353f80,
0x3f460000,0x3f223f80,0x3f7f3f35,0xbdc93f35,0x3ef13f7b,0xbf62be48,0xbe953f0e,0xbf75bf55,0xbf75bec4,0xbe95bf6d,0xbf62bf6d,0x3ef1bec4,
0xbdc9bf55,0x3f7f3f0e,0x3f22be48,0x3f463f7b,0xbf0ebf80,0x3f550000,0x3f550000,0x3f0e3f80,0x3f7b3ec4,0x3e483f6d,0x3e483f6d,0xbf7bbec4,
0xbe483f35,0xbf7bbf35,0xbf7bbf35,0x3e48bf35,0xbf55bf6d,0x3f0ebec4,0x3f0ebec4,0x3f553f6d,0xbf620000,0xbef1bf80,0x3e95bf35,0x3f753f35,
0x3dc9bf55,0x3f7f3f0e,0x3f223f7b,0xbf463e48,0x3f463f6d,0xbf223ec4,0xbf7fbec4,0xbdc9bf6d,0xbf75be48,0xbe95bf7b,0x3ef1bf0e,0x3f623f55,
0x3ec43f80,0xbf6d0000,0xbec4bf80,0x3f6d0000,0xbf6dbf35,0x3ec4bf35,0x3f6d3f35,0xbec43f35,0x3f6d0000,0x3ec43f80,0xbf6d0000,0xbec4bf80,
0xbec43f35,0xbf6dbf35,0x3ec4bf35,0x3f6d3f35,0x3f750000,0x3e953f80,0xbf62bf35,0x3ef1bf35,0xbf223f0e,0xbf46bf55,0x3f7f3e48,0x3dc93f7b,
0x3dc9bf6d,0x3f7f3ec4,0xbf463ec4,0xbf22bf6d,0x3ef13f7b,0xbf623e48,0x3e95bf55,0x3f753f0e,0xbe48bf80,0x3f7b0000,0xbf7b0000,0xbe48bf80,
0x3f0e3f6d,0xbf553ec4,0x3f55bec4,0x3f0e3f6d,0xbf55bf35,0x3f0ebf35,0xbf0e3f35,0xbf55bf35,0x3f7b3ec4,0xbe483f6d,0x3e48bf6d,0x3f7b3ec4,
0xbf7f0000,0xbdc9bf80,0xbf223f35,0xbf46bf35,0x3f75be48,0x3e953f7b,0x3ef1bf55,0x3f623f0e,0xbf623ec4,0xbef1bf6d,0xbe953f6d,0xbf75bec4,
0x3f46bf0e,0x3f223f55,0x3dc9bf7b,0x3f7f3e48,0x3f80,0xbf800000,0x3f80,0xbf800000,0xbf80,0x3f800000,0xbf80,0x3f800000,
0x3f80,0xbf800000,0x3f80,0xbf800000,0xbf80,0x3f800000,0xbf80,0x3f800000,0x3f7f0000,0xbdc93f80,0x3f223f35,0xbf463f35,
0xbf75be48,0x3e95bf7b,0xbef1bf55,0x3f62bf0e,0x3f623ec4,0xbef13f6d,0x3e953f6d,0xbf753ec4,0xbf46bf0e,0x3f22bf55,0xbdc9bf7b,0x3f7fbe48,
0x3e48bf80,0x3f7b0000,0x3f7b0000,0xbe483f80,0xbf0e3f6d,0xbf55bec4,0xbf55bec4,0x3f0ebf6d,0x3f55bf35,0x3f0e3f35,0x3f0e3f35,0xbf553f35,
0xbf7b3ec4,0xbe48bf6d,0xbe48bf6d,0x3f7bbec4,0xbf750000,0x3e95bf80,0x3f62bf35,0x3ef13f35,0x3f223f0e,0xbf463f55,0xbf7f3e48,0x3dc9bf7b,
0xbdc9bf6d,0x3f7fbec4,0x3f463ec4,0xbf223f6d,0xbef13f7b,0xbf62be48,0xbe95bf55,0x3f75bf0e,0xbec43f80,0xbf6d0000,0x3ec4bf80,0x3f6d0000,
0x3f6dbf35,0x3ec43f35,0xbf6d3f35,0xbec4bf35,0xbf6d0000,0x3ec4bf80,0x3f6d0000,0xbec43f80,0x3ec43f35,0xbf6d3f35,0xbec4bf35,0x3f6dbf35,
0x3f620000,0xbef13f80,0xbe95bf35,0x3f75bf35,0xbdc9bf55,0x3f7fbf0e,0xbf223f7b,0xbf46be48,0xbf463f6d,0xbf22bec4,0x3f7fbec4,0xbdc93f6d,
0x3f75be48,0xbe953f7b,0xbef1bf0e,0x3f62bf55,0x3f0ebf80,0x3f550000,0xbf550000,0x3f0ebf80,0xbf7b3ec4,0x3e48bf6d,0xbe483f6d,0xbf7b3ec4,
0x3e483f35,0xbf7b3f35,0x3f7bbf35,0x3e483f35,0x3f55bf6d,0x3f0e3ec4,0xbf0ebec4,0x3f55bf6d,0xbf460000,0x3f22bf80,0xbf7f3f35,0xbdc9bf35,
0xbef13f7b,0xbf623e48,0x3e953f0e,0xbf753f55,0x3f75bec4,0xbe953f6d,0x3f62bf6d,0x3ef13ec4,0x3dc9bf55,0x3f7fbf0e,0xbf22be48,0x3f46bf7b,
0xbf353f80,0xbf350000,0xbf353f80,0xbf350000,0x3f350000,0xbf353f80,0x3f350000,0xbf353f80,0x3f35bf80,0x3f350000,0x3f35bf80,0x3f350000,
0xbf350000,0x3f35bf80,0xbf350000,0x3f35bf80,0x3f220000,0xbf463f80,0xbdc93f35,0xbf7f3f35,0x3f62bf7b,0x3ef13e48,0x3f75bf0e,0xbe953f55,
0xbe95bec4,0x3f75bf6d,0x3ef1bf6d,0x3f62bec4,0xbf7f3f55,0xbdc9bf0e,0xbf463e48,0x3f22bf7b,0x3f55bf80,0x3f0e0000,0x3f0e0000,0xbf553f80,
0xbe48bec4,0x3f7bbf6d,0x3f7bbf6d,0x3e483ec4,0xbf7b3f35,0x3e48bf35,0x3e48bf35,0x3f7bbf35,0xbf0e3f6d,0xbf553ec4,0xbf553ec4,0x3f0ebf6d,
0xbef10000,0x3f62bf80,0x3f75bf35,0xbe953f35,0xbf7f3f55,0x3dc9bf0e,0x3f46bf7b,0x3f22be48,0xbf223f6d,0xbf463ec4,0xbdc9bec4,0x3f7fbf6d,
0x3e953e48,0xbf753f7b,0xbf623f0e,0x3ef1bf55,0xbf6d3f80,0xbec40000,0x3f6dbf80,0x3ec40000,0xbec43f35,0xbf6d3f35,0x3ec4bf35,0x3f6dbf35,
0x3ec40000,0xbf6d3f80,0xbec40000,0x3f6dbf80,0x3f6dbf35,0xbec43f35,0xbf6d3f35,0x3ec4bf35,0x3e950000,0xbf753f80,0x3ef1bf35,0x3f62bf35,
0x3f46bf0e,0xbf223f55,0xbdc9be48,0x3f7fbf7b,0x3f7fbf6d,0xbdc93ec4,0xbf223ec4,0x3f46bf6d,0x3f62bf7b,0x3ef1be48,0xbf753f55,0x3e95bf0e,
0x3f7bbf80,0x3e480000,0xbe480000,0x3f7bbf80,0x3f55bf6d,0x3f0ebec4,0xbf0e3ec4,0x3f55bf6d,0x3f0ebf35,0x3f55bf35,0xbf553f35,0x3f0ebf35,
0x3e48bec4,0x3f7bbf6d,0xbf7b3f6d,0x3e48bec4,0xbdc90000,0x3f7fbf80,0xbf463f35,0x3f22bf35,0xbe953e48,0x3f75bf7b,0xbf623f55,0x3ef1bf0e,
0xbef13ec4,0x3f62bf6d,0xbf753f6d,0x3e95bec4,0xbf223f0e,0x3f46bf55,0xbf7f3f7b,0x3dc9be48,0x40003f80,0x3fb53f80,0x3f80,0xbfb53f80,
0x40004000,0xbfb50000,0x0,0xbfb5c000,0x40004000,0xbfb5c000,0x0,0x3fb50000,0x40004000,0x3fb50000,0x0,0x3fb54000,
0x3fff3f80,0x3fa23f80,0xbe49bf80,0xbfc6bf80,0x3ff53ffb,0xbfe2bec8,0xbf15bec8,0xbf71bffb,0x3fe23fed,0xbf15bfed,0xbf71bf44,0x3ff53f44,
0x3fc63fd5,0x3fff3f8e,0xbfa2bf8e,0x3e493fd5,0x3ffb3f80,0x3f8e3f80,0xbec83f80,0xbfd53f80,0x3fd53fed,0xbffbbf44,0xbf8ebf44,0xbec8bfed,
0x3f8e3fb5,0x3ec8bfb5,0xbfd5bfb5,0x3ffb3fb5,0x3ec83f44,0x3fd53fed,0xbffbbfed,0xbf8e3f44,0x3ff53f80,0x3f713f80,0xbf15bf80,0xbfe2bf80,
0x3fa23fd5,0xbfffbf8e,0xbfc6bf8e,0x3e49bfd5,0x3e493f44,0x3fa2bf44,0xbfffbfed,0x3fc63fed,0xbf71bec8,0x3f153ffb,0xbfe2bffb,0xbff5bec8,
0x3fed3f80,0x3f443f80,0xbf443f80,0xbfed3f80,0x3f443fb5,0xbfedbfb5,0xbfedbfb5,0x3f44bfb5,0xbf440000,0x3fed0000,0xbfedc000,0x3f444000,
0xbfedbfb5,0xbf443fb5,0xbf44bfb5,0xbfedbfb5,0x3fe23f80,0x3f153f80,0xbf71bf80,0xbff5bf80,0x3e493f8e,0xbfc6bfd5,0xbfffbfd5,0x3fa2bf8e,
0xbfc6bf44,0x3fff3f44,0xbfa2bfed,0xbe493fed,0xbff5bffb,0xbfe23ec8,0x3f15bec8,0xbf71bffb,0x3fd53f80,0x3ec83f80,0xbf8e3f80,0xbffb3f80,
0xbec83f44,0xbf8ebfed,0xbffbbfed,0x3fd5bf44,0xbffbbfb5,0x3fd53fb5,0xbec8bfb5,0xbf8e3fb5,0xbf8ebfed,0xbffbbf44,0x3fd53f44,0x3ec8bfed,
0x3fc63f80,0x3e493f80,0xbfa2bf80,0xbfffbf80,0xbf713ec8,0xbf15bffb,0xbfe2bffb,0x3ff5bec8,0xbff5bfed,0x3f713fed,0x3f15bf44,0xbfe23f44,
0x3e49bf8e,0xbfa2bfd5,0x3fff3fd5,0x3fc6bf8e,0x3f80,0xbfb53f80,0xc0003f80,0xbfb53f80,0xc000,0x3fb50000,0x40000000,0xbfb54000,
0x4000,0x3fb5c000,0xc0000000,0x3fb50000,0xc000,0xbfb50000,0x40000000,0x3fb5c000,0xbe493f80,0xbfc63f80,0xbfffbf80,0xbfa2bf80,
0x3f15bffb,0x3f713ec8,0x3ff53ec8,0xbfe23ffb,0xbf713fed,0x3ff5bfed,0xbfe2bf44,0x3f153f44,0x3fa2bfd5,0xbe49bf8e,0x3fc63f8e,0x3fffbfd5,
0xbec83f80,0xbfd53f80,0xbffb3f80,0xbf8e3f80,0x3f8ebfed,0x3ec83f44,0x3fd53f44,0xbffb3fed,0xbfd53fb5,0x3ffbbfb5,0xbf8ebfb5,0xbec83fb5,
0x3ffbbf44,0x3f8ebfed,0x3ec83fed,0x3fd5bf44,0xbf153f80,0xbfe23f80,0xbff5bf80,0xbf71bf80,0x3fc6bfd5,0xbe493f8e,0x3fa23f8e,0xbfff3fd5,
0xbfff3f44,0x3fc6bf44,0xbe49bfed,0xbfa23fed,0x3fe23ec8,0x3ff5bffb,0xbf713ffb,0x3f153ec8,0xbf443f80,0xbfed3f80,0xbfed3f80,0xbf443f80,
0x3fedbfb5,0xbf443fb5,0x3f443fb5,0xbfed3fb5,0xbfed0000,0x3f440000,0x3f44c000,0xbfed4000,0x3f443fb5,0x3fedbfb5,0xbfed3fb5,0xbf443fb5,
0xbf713f80,0xbff53f80,0xbfe2bf80,0xbf15bf80,0x3fffbf8e,0xbfa23fd5,0x3e493fd5,0xbfc63f8e,0xbfa2bf44,0xbe493f44,0x3fc6bfed,0xbfff3fed,
0xbf153ffb,0x3f71bec8,0xbff53ec8,0xbfe23ffb,0xbf8e3f80,0xbffb3f80,0xbfd53f80,0xbec83f80,0x3ffbbf44,0xbfd53fed,0xbec83fed,0xbf8e3f44,
0xbec8bfb5,0xbf8e3fb5,0x3ffbbfb5,0xbfd53fb5,0xbfd53fed,0xbec83f44,0xbf8ebf44,0xbffb3fed,0xbfa23f80,0xbfff3f80,0xbfc6bf80,0xbe49bf80,
0x3fe2bec8,0xbff53ffb,0xbf713ffb,0xbf153ec8,0x3f15bfed,0xbfe23fed,0x3ff5bf44,0xbf713f44,0xbfff3f8e,0xbfc63fd5,0x3e49bfd5,0xbfa23f8e,
0xc0003f80,0xbfb53f80,0x3f80,0x3fb53f80,0xc0004000,0x3fb50000,0x0,0x3fb5c000,0xc0004000,0x3fb5c000,0x0,0xbfb50000,
0xc0004000,0xbfb50000,0x0,0xbfb54000,0xbfff3f80,0xbfa23f80,0x3e49bf80,0x3fc6bf80,0xbff53ffb,0x3fe2bec8,0x3f15bec8,0x3f71bffb,
0xbfe23fed,0x3f15bfed,0x3f71bf44,0xbff53f44,0xbfc63fd5,0xbfff3f8e,0x3fa2bf8e,0xbe493fd5,0xbffb3f80,0xbf8e3f80,0x3ec83f80,0x3fd53f80,
0xbfd53fed,0x3ffbbf44,0x3f8ebf44,0x3ec8bfed,0xbf8e3fb5,0xbec8bfb5,0x3fd5bfb5,0xbffb3fb5,0xbec83f44,0xbfd53fed,0x3ffbbfed,0x3f8e3f44,
0xbff53f80,0xbf713f80,0x3f15bf80,0x3fe2bf80,0xbfa23fd5,0x3fffbf8e,0x3fc6bf8e,0xbe49bfd5,0xbe493f44,0xbfa2bf44,0x3fffbfed,0xbfc63fed,
0x3f71bec8,0xbf153ffb,0x3fe2bffb,0x3ff5bec8,0xbfed3f80,0xbf443f80,0x3f443f80,0x3fed3f80,0xbf443fb5,0x3fedbfb5,0x3fedbfb5,0xbf44bfb5,
0x3f440000,0xbfed0000,0x3fedc000,0xbf444000,0x3fedbfb5,0x3f443fb5,0x3f44bfb5,0x3fedbfb5,0xbfe23f80,0xbf153f80,0x3f71bf80,0x3ff5bf80,
0xbe493f8e,0x3fc6bfd5,0x3fffbfd5,0xbfa2bf8e,0x3fc6bf44,0xbfff3f44,0x3fa2bfed,0x3e493fed,0x3ff5bffb,0x3fe23ec8,0xbf15bec8,0x3f71bffb,
0xbfd53f80,0xbec83f80,0x3f8e3f80,0x3ffb3f80,0x3ec83f44,0x3f8ebfed,0x3ffbbfed,0xbfd5bf44,0x3ffbbfb5,0xbfd53fb5,0x3ec8bfb5,0x3f8e3fb5,
0x3f8ebfed,0x3ffbbf44,0xbfd53f44,0xbec8bfed,0xbfc63f80,0xbe493f80,0x3fa2bf80,0x3fffbf80,0x3f713ec8,0x3f15bffb,0x3fe2bffb,0xbff5bec8,
0x3ff5bfed,0xbf713fed,0xbf15bf44,0x3fe23f44,0xbe49bf8e,0x3fa2bfd5,0xbfff3fd5,0xbfc6bf8e,0x3f80,0x3fb53f80,0x40003f80,0x3fb53f80,
0xc000,0xbfb50000,0xc0000000,0x3fb54000,0x4000,0xbfb5c000,0x40000000,0xbfb50000,0xc000,0x3fb50000,0xc0000000,0xbfb5c000,
0x3e493f80,0x3fc63f80,0x3fffbf80,0x3fa2bf80,0xbf15bffb,0xbf713ec8,0xbff53ec8,0x3fe23ffb,0x3f713fed,0xbff5bfed,0x3fe2bf44,0xbf153f44,
0xbfa2bfd5,0x3e49bf8e,0xbfc63f8e,0xbfffbfd5,0x3ec83f80,0x3fd53f80,0x3ffb3f80,0x3f8e3f80,0xbf8ebfed,0xbec83f44,0xbfd53f44,0x3ffb3fed,
0x3fd53fb5,0xbffbbfb5,0x3f8ebfb5,0x3ec83fb5,0xbffbbf44,0xbf8ebfed,0xbec83fed,0xbfd5bf44,0x3f153f80,0x3fe23f80,0x3ff5bf80,0x3f71bf80,
0xbfc6bfd5,0x3e493f8e,0xbfa23f8e,0x3fff3fd5,0x3fff3f44,0xbfc6bf44,0x3e49bfed,0x3fa23fed,0xbfe23ec8,0xbff5bffb,0x3f713ffb,0xbf153ec8,
0x3f443f80,0x3fed3f80,0x3fed3f80,0x3f443f80,0xbfedbfb5,0x3f443fb5,0xbf443fb5,0x3fed3fb5,0x3fed0000,0xbf440000,0xbf44c000,0x3fed4000,
0xbf443fb5,0xbfedbfb5,0x3fed3fb5,0x3f443fb5,0x3f713f80,0x3ff53f80,0x3fe2bf80,0x3f15bf80,0xbfffbf8e,0x3fa23fd5,0xbe493fd5,0x3fc63f8e,
0x3fa2bf44,0x3e493f44,0xbfc6bfed,0x3fff3fed,0x3f153ffb,0xbf71bec8,0x3ff53ec8,0x3fe23ffb,0x3f8e3f80,0x3ffb3f80,0x3fd53f80,0x3ec83f80,
0xbffbbf44,0x3fd53fed,0x3ec83fed,0x3f8e3f44,0x3ec8bfb5,0x3f8e3fb5,0xbffbbfb5,0x3fd53fb5,0x3fd53fed,0x3ec83f44,0x3f8ebf44,0x3ffb3fed,
0x3fa23f80,0x3fff3f80,0x3fc6bf80,0x3e49bf80,0xbfe2bec8,0x3ff53ffb,0x3f713ffb,0x3f153ec8,0xbf15bfed,0x3fe23fed,0xbff5bf44,0x3f713f44,
0x3fff3f8e,0x3fc63fd5,0xbe49bfd5,0x3fa23f8e,0x40004000,0x3fb54000,0x0,0xbfb50000,0x40004000,0xbfb50000,0x0,0xbfb5c000,
0x40004000,0xbfb5c000,0x0,0x3fb50000,0x40004000,0x3fb50000,0x0,0x3fb54000,0x3fa23fb5,0xbe493fb5,0xbfc6bfb5,0xbfffbfb5,
0x3f713f8e,0xbff5bfd5,0xbfe2bfd5,0x3f15bf8e,0x3f153f44,0x3f71bf44,0xbff5bfed,0x3fe23fed,0x3e493ec8,0x3fc63ffb,0xbfffbffb,0xbfa23ec8,
0xbec80000,0xbfd50000,0xbffbc000,0xbf8ec000,0xbf8ebf44,0xbec8bfed,0xbfd5bfed,0x3ffb3f44,0xbfd5bfb5,0x3ffb3fb5,0xbf8ebfb5,0xbec83fb5,
0xbffbbfed,0xbf8e3f44,0xbec8bf44,0xbfd5bfed,0xbfe2bfb5,0xbff5bfb5,0xbf71bfb5,0x3f15bfb5,0xbfffbffb,0x3fc6bec8,0x3e49bec8,0x3fa23ffb,
0xbfc6bfed,0x3e493fed,0x3fa23f44,0xbfffbf44,0xbf15bf8e,0xbfe2bfd5,0x3ff53fd5,0x3f71bf8e,0xbfedc000,0xbf44c000,0x3f440000,0x3fed0000,
0xbf44bfb5,0x3fed3fb5,0x3fed3fb5,0xbf443fb5,0x3f440000,0xbfed0000,0x3fed4000,0xbf44c000,0x3fed3fb5,0x3f44bfb5,0x3f443fb5,0x3fed3fb5,
0xbf15bfb5,0x3f71bfb5,0x3ff53fb5,0x3fe23fb5,0x3fa23ec8,0x3e493ffb,0x3fc63ffb,0xbfffbec8,0x3fff3fed,0xbfa2bfed,0xbe493f44,0x3fc6bf44,
0x3f713fd5,0x3ff53f8e,0xbfe2bf8e,0xbf153fd5,0x3f8e0000,0x3ffb0000,0x3fd54000,0x3ec84000,0x3ffb3fed,0xbfd53f44,0xbec83f44,0xbf8ebfed,
0x3ec83fb5,0x3f8ebfb5,0xbffbbfb5,0x3fd53fb5,0xbfd5bf44,0xbec83fed,0xbf8ebfed,0xbffbbf44,0x3fff3fb5,0x3fc63fb5,0x3e493fb5,0xbfa23fb5,
0x3f153fd5,0xbfe2bf8e,0xbff5bf8e,0x3f71bfd5,0xbfe2bf44,0x3ff53f44,0xbf71bfed,0xbf153fed,0xbfa2bffb,0xbfffbec8,0x3fc63ec8,0x3e49bffb,
0x4000,0xbfb54000,0xc0000000,0xbfb50000,0xc000,0x3fb50000,0x40000000,0xbfb54000,0x4000,0x3fb5c000,0xc0000000,0x3fb50000,
0xc000,0xbfb50000,0x40000000,0x3fb5c000,0xbfc63fb5,0xbfff3fb5,0xbfa2bfb5,0x3e49bfb5,0x3fe2bf8e,0xbf153fd5,0x3f713fd5,0xbff53f8e,
0xbff53f44,0x3fe2bf44,0xbf15bfed,0xbf713fed,0x3fffbec8,0x3fa2bffb,0x3e493ffb,0x3fc6bec8,0xbffb0000,0xbf8e0000,0x3ec8c000,0x3fd5c000,
0x3fd53f44,0xbffb3fed,0xbf8e3fed,0xbec8bf44,0xbf8ebfb5,0xbec83fb5,0x3fd5bfb5,0xbffb3fb5,0x3ec83fed,0x3fd5bf44,0xbffb3f44,0xbf8e3fed,
0xbf71bfb5,0x3f15bfb5,0x3fe2bfb5,0x3ff5bfb5,0xbe493ffb,0xbfa23ec8,0xbfff3ec8,0x3fc6bffb,0x3fa2bfed,0xbfff3fed,0x3fc63f44,0xbe49bf44,
0xbff53f8e,0xbf713fd5,0xbf15bfd5,0xbfe23f8e,0x3f44c000,0x3fedc000,0x3fed0000,0x3f440000,0xbfed3fb5,0x3f44bfb5,0xbf44bfb5,0x3fedbfb5,
0x3fed0000,0xbf440000,0xbf444000,0x3fedc000,0xbf44bfb5,0xbfed3fb5,0x3fedbfb5,0x3f44bfb5,0x3ff5bfb5,0x3fe2bfb5,0x3f153fb5,0xbf713fb5,
0xbfc6bec8,0x3fffbffb,0x3fa2bffb,0x3e493ec8,0xbe493fed,0x3fc6bfed,0xbfff3f44,0x3fa2bf44,0x3fe2bfd5,0x3f15bf8e,0x3f713f8e,0x3ff5bfd5,
0x3fd50000,0x3ec80000,0xbf8e4000,0xbffb4000,0x3ec8bfed,0x3f8ebf44,0x3ffbbf44,0xbfd53fed,0xbffb3fb5,0x3fd5bfb5,0xbec8bfb5,0xbf8e3fb5,
0x3f8e3f44,0x3ffbbfed,0xbfd53fed,0xbec83f44,0x3e493fb5,0xbfa23fb5,0xbfff3fb5,0xbfc63fb5,0x3ff5bfd5,0xbf713f8e,0x3f153f8e,0xbfe23fd5,
0xbf71bf44,0xbf153f44,0x3fe2bfed,0xbff53fed,0xbfc63ffb,0xbe493ec8,0xbfa2bec8,0xbfff3ffb,0xc0004000,0xbfb54000,0x0,0x3fb50000,
0xc0004000,0x3fb50000,0x0,0x3fb5c000,0xc0004000,0x3fb5c000,0x0,0xbfb50000,0xc0004000,0xbfb50000,0x0,0xbfb54000,
0xbfa23fb5,0x3e493fb5,0x3fc6bfb5,0x3fffbfb5,0xbf713f8e,0x3ff5bfd5,0x3fe2bfd5,0xbf15bf8e,0xbf153f44,0xbf71bf44,0x3ff5bfed,0xbfe23fed,
0xbe493ec8,0xbfc63ffb,0x3fffbffb,0x3fa23ec8,0x3ec80000,0x3fd50000,0x3ffbc000,0x3f8ec000,0x3f8ebf44,0x3ec8bfed,0x3fd5bfed,0xbffb3f44,
0x3fd5bfb5,0xbffb3fb5,0x3f8ebfb5,0x3ec83fb5,0x3ffbbfed,0x3f8e3f44,0x3ec8bf44,0x3fd5bfed,0x3fe2bfb5,0x3ff5bfb5,0x3f71bfb5,0xbf15bfb5,
0x3fffbffb,0xbfc6bec8,0xbe49bec8,0xbfa23ffb,0x3fc6bfed,0xbe493fed,0xbfa23f44,0x3fffbf44,0x3f15bf8e,0x3fe2bfd5,0xbff53fd5,0xbf71bf8e,
0x3fedc000,0x3f44c000,0xbf440000,0xbfed0000,0x3f44bfb5,0xbfed3fb5,0xbfed3fb5,0x3f443fb5,0xbf440000,0x3fed0000,0xbfed4000,0x3f44c000,
0xbfed3fb5,0xbf44bfb5,0xbf443fb5,0xbfed3fb5,0x3f15bfb5,0xbf71bfb5,0xbff53fb5,0xbfe23fb5,0xbfa23ec8,0xbe493ffb,0xbfc63ffb,0x3fffbec8,
0xbfff3fed,0x3fa2bfed,0x3e493f44,0xbfc6bf44,0xbf713fd5,0xbff53f8e,0x3fe2bf8e,0x3f153fd5,0xbf8e0000,0xbffb0000,0xbfd54000,0xbec84000,
0xbffb3fed,0x3fd53f44,0x3ec83f44,0x3f8ebfed,0xbec83fb5,0xbf8ebfb5,0x3ffbbfb5,0xbfd53fb5,0x3fd5bf44,0x3ec83fed,0x3f8ebfed,0x3ffbbf44,
0xbfff3fb5,0xbfc63fb5,0xbe493fb5,0x3fa23fb5,0xbf153fd5,0x3fe2bf8e,0x3ff5bf8e,0xbf71bfd5,0x3fe2bf44,0xbff53f44,0x3f71bfed,0x3f153fed,
0x3fa2bffb,0x3fffbec8,0xbfc63ec8,0xbe49bffb,0x4000,0x3fb54000,0x40000000,0x3fb50000,0xc000,0xbfb50000,0xc0000000,0x3fb54000,
0x4000,0xbfb5c000,0x40000000,0xbfb50000,0xc000,0x3fb50000,0xc0000000,0xbfb5c000,0x3fc63fb5,0x3fff3fb5,0x3fa2bfb5,0xbe49bfb5,
0xbfe2bf8e,0x3f153fd5,0xbf713fd5,0x3ff53f8e,0x3ff53f44,0xbfe2bf44,0x3f15bfed,0x3f713fed,0xbfffbec8,0xbfa2bffb,0xbe493ffb,0xbfc6bec8,
0x3ffb0000,0x3f8e0000,0xbec8c000,0xbfd5c000,0xbfd53f44,0x3ffb3fed,0x3f8e3fed,0x3ec8bf44,0x3f8ebfb5,0x3ec83fb5,0xbfd5bfb5,0x3ffb3fb5,
0xbec83fed,0xbfd5bf44,0x3ffb3f44,0x3f8e3fed,0x3f71bfb5,0xbf15bfb5,0xbfe2bfb5,0xbff5bfb5,0x3e493ffb,0x3fa23ec8,0x3fff3ec8,0xbfc6bffb,
0xbfa2bfed,0x3fff3fed,0xbfc63f44,0x3e49bf44,0x3ff53f8e,0x3f713fd5,0x3f15bfd5,0x3fe23f8e,0xbf44c000,0xbfedc000,0xbfed0000,0xbf440000,
0x3fed3fb5,0xbf44bfb5,0x3f44bfb5,0xbfedbfb5,0xbfed0000,0x3f440000,0x3f444000,0xbfedc000,0x3f44bfb5,0x3fed3fb5,0xbfedbfb5,0xbf44bfb5,
0xbff5bfb5,0xbfe2bfb5,0xbf153fb5,0x3f713fb5,0x3fc6bec8,0xbfffbffb,0xbfa2bffb,0xbe493ec8,0x3e493fed,0xbfc6bfed,0x3fff3f44,0xbfa2bf44,
0xbfe2bfd5,0xbf15bf8e,0xbf713f8e,0xbff5bfd5,0xbfd50000,0xbec80000,0x3f8e4000,0x3ffb4000,0xbec8bfed,0xbf8ebf44,0xbffbbf44,0x3fd53fed,
0x3ffb3fb5,0xbfd5bfb5,0x3ec8bfb5,0x3f8e3fb5,0xbf8e3f44,0xbffbbfed,0x3fd53fed,0x3ec83f44,0xbe493fb5,0x3fa23fb5,0x3fff3fb5,0x3fc63fb5,
0xbff5bfd5,0x3f713f8e,0xbf153f8e,0x3fe23fd5,0x3f71bf44,0x3f153f44,0xbfe2bfed,0x3ff53fed,0x3fc63ffb,0x3e493ec8,0x3fa2bec8,0x3fff3ffb,
0x40004000,0x3fb54000,0x0,0xbfb50000,0x40004000,0xbfb50000,0x0,0xbfb5c000,0x40004000,0xbfb5c000,0x0,0x3fb50000,
0x40004000,0x3fb50000,0x0,0x3fb54000,0xbe490000,0xbfc60000,0xbfffc000,0xbfa2c000,0xbf15bec8,0xbf71bffb,0xbff5bffb,0x3fe23ec8,
0xbf71bf44,0x3ff53f44,0xbfe2bfed,0x3f153fed,0xbfa2bf8e,0x3e493fd5,0xbfc6bfd5,0xbfffbf8e,0xbffbc000,0xbf8ec000,0x3ec80000,0x3fd50000,
0xbfd5bfed,0x3ffb3f44,0x3f8e3f44,0x3ec83fed,0xbf8ebfb5,0xbec83fb5,0x3fd53fb5,0xbffbbfb5,0xbec8bf44,0xbfd5bfed,0x3ffb3fed,0x3f8ebf44,
0x3f150000,0x3fe20000,0x3ff54000,0x3f714000,0x3fc63f8e,0xbe493fd5,0x3fa23fd5,0xbfffbf8e,0x3fff3fed,0xbfc6bfed,0x3e493f44,0x3fa2bf44,
0x3fe23ffb,0x3ff53ec8,0xbf71bec8,0x3f153ffb,0x3fed4000,0x3f444000,0xbf440000,0xbfed0000,0x3f443fb5,0xbfedbfb5,0xbfedbfb5,0x3f44bfb5,
0xbf440000,0x3fed0000,0xbfedc000,0x3f444000,0xbfedbfb5,0xbf443fb5,0xbf44bfb5,0xbfedbfb5,0xbf710000,0xbff50000,0xbfe2c000,0xbf15c000,
0xbfffbfd5,0x3fa2bf8e,0xbe49bf8e,0x3fc63fd5,0xbfa2bfed,0xbe493fed,0x3fc63f44,0xbfffbf44,0x3f15bec8,0xbf71bffb,0x3ff53ffb,0x3fe2bec8,
0xbfd5c000,0xbec8c000,0x3f8e0000,0x3ffb0000,0x3ec8bf44,0x3f8e3fed,0x3ffb3fed,0xbfd53f44,0x3ffb3fb5,0xbfd5bfb5,0x3ec83fb5,0x3f8ebfb5,
0x3f8e3fed,0x3ffb3f44,0xbfd5bf44,0xbec83fed,0x3fa20000,0x3fff0000,0x3fc64000,0x3e494000,0x3fe23ffb,0xbff53ec8,0xbf713ec8,0xbf15bffb,
0xbf153f44,0x3fe2bf44,0xbff5bfed,0x3f713fed,0xbfffbfd5,0xbfc63f8e,0x3e49bf8e,0xbfa2bfd5,0x4000,0xbfb54000,0xc0000000,0xbfb50000,
0xc000,0x3fb50000,0x40000000,0xbfb54000,0x4000,0x3fb5c000,0xc0000000,0x3fb50000,0xc000,0xbfb50000,0x40000000,0x3fb5c000,
0xbfff0000,0xbfa20000,0x3e49c000,0x3fc6c000,0x3ff53ec8,0xbfe23ffb,0xbf153ffb,0xbf71bec8,0xbfe2bf44,0x3f153f44,0x3f71bfed,0xbff53fed,
0x3fc63f8e,0x3fffbfd5,0xbfa23fd5,0x3e493f8e,0x3ec8c000,0x3fd5c000,0x3ffb0000,0x3f8e0000,0xbf8e3fed,0xbec8bf44,0xbfd5bf44,0x3ffbbfed,
0x3fd5bfb5,0xbffb3fb5,0x3f8e3fb5,0x3ec8bfb5,0xbffb3f44,0xbf8e3fed,0xbec8bfed,0xbfd53f44,0x3ff50000,0x3f710000,0xbf154000,0xbfe24000,
0xbfa2bf8e,0x3fffbfd5,0x3fc6bfd5,0xbe493f8e,0x3e493fed,0x3fa2bfed,0xbfff3f44,0x3fc6bf44,0x3f71bffb,0xbf15bec8,0x3fe23ec8,0x3ff5bffb,
0xbf444000,0xbfed4000,0xbfed0000,0xbf440000,0x3fedbfb5,0xbf443fb5,0x3f443fb5,0xbfed3fb5,0xbfed0000,0x3f440000,0x3f44c000,0xbfed4000,
0x3f443fb5,0x3fedbfb5,0xbfed3fb5,0xbf443fb5,0xbfe20000,0xbf150000,0x3f71c000,0x3ff5c000,0x3e493fd5,0xbfc63f8e,0xbfff3f8e,0x3fa2bfd5,
0x3fc6bfed,0xbfff3fed,0x3fa23f44,0x3e49bf44,0xbff53ec8,0xbfe23ffb,0x3f15bffb,0xbf713ec8,0x3f8ec000,0x3ffbc000,0x3fd50000,0x3ec80000,
0xbffb3f44,0x3fd5bfed,0x3ec8bfed,0x3f8ebf44,0x3ec83fb5,0x3f8ebfb5,0xbffb3fb5,0x3fd5bfb5,0x3fd5bfed,0x3ec8bf44,0x3f8e3f44,0x3ffbbfed,
0x3fc60000,0x3e490000,0xbfa24000,0xbfff4000,0x3f71bffb,0x3f15bec8,0x3fe2bec8,0xbff53ffb,0xbff53f44,0x3f71bf44,0x3f15bfed,0xbfe23fed,
0xbe493fd5,0x3fa2bf8e,0xbfff3f8e,0xbfc63fd5,0xc0004000,0xbfb54000,0x0,0x3fb50000,0xc0004000,0x3fb50000,0x0,0x3fb5c000,
0xc0004000,0x3fb5c000,0x0,0xbfb50000,0xc0004000,0xbfb50000,0x0,0xbfb54000,0x3e490000,0x3fc60000,0x3fffc000,0x3fa2c000,
0x3f15bec8,0x3f71bffb,0x3ff5bffb,0xbfe23ec8,0x3f71bf44,0xbff53f44,0x3fe2bfed,0xbf153fed,0x3fa2bf8e,0xbe493fd5,0x3fc6bfd5,0x3fffbf8e,
0x3ffbc000,0x3f8ec000,0xbec80000,0xbfd50000,0x3fd5bfed,0xbffb3f44,0xbf8e3f44,0xbec83fed,0x3f8ebfb5,0x3ec83fb5,0xbfd53fb5,0x3ffbbfb5,
0x3ec8bf44,0x3fd5bfed,0xbffb3fed,0xbf8ebf44,0xbf150000,0xbfe20000,0xbff54000,0xbf714000,0xbfc63f8e,0x3e493fd5,0xbfa23fd5,0x3fffbf8e,
0xbfff3fed,0x3fc6bfed,0xbe493f44,0xbfa2bf44,0xbfe23ffb,0xbff53ec8,0x3f71bec8,0xbf153ffb,0xbfed4000,0xbf444000,0x3f440000,0x3fed0000,
0xbf443fb5,0x3fedbfb5,0x3fedbfb5,0xbf44bfb5,0x3f440000,0xbfed0000,0x3fedc000,0xbf444000,0x3fedbfb5,0x3f443fb5,0x3f44bfb5,0x3fedbfb5,
0x3f710000,0x3ff50000,0x3fe2c000,0x3f15c000,0x3fffbfd5,0xbfa2bf8e,0x3e49bf8e,0xbfc63fd5,0x3fa2bfed,0x3e493fed,0xbfc63f44,0x3fffbf44,
0xbf15bec8,0x3f71bffb,0xbff53ffb,0xbfe2bec8,0x3fd5c000,0x3ec8c000,0xbf8e0000,0xbffb0000,0xbec8bf44,0xbf8e3fed,0xbffb3fed,0x3fd53f44,
0xbffb3fb5,0x3fd5bfb5,0xbec83fb5,0xbf8ebfb5,0xbf8e3fed,0xbffb3f44,0x3fd5bf44,0x3ec83fed,0xbfa20000,0xbfff0000,0xbfc64000,0xbe494000,
0xbfe23ffb,0x3ff53ec8,0x3f713ec8,0x3f15bffb,0x3f153f44,0xbfe2bf44,0x3ff5bfed,0xbf713fed,0x3fffbfd5,0x3fc63f8e,0xbe49bf8e,0x3fa2bfd5,
0x4000,0x3fb54000,0x40000000,0x3fb50000,0xc000,0xbfb50000,0xc0000000,0x3fb54000,0x4000,0xbfb5c000,0x40000000,0xbfb50000,
0xc000,0x3fb50000,0xc0000000,0xbfb5c000,0x3fff0000,0x3fa20000,0xbe49c000,0xbfc6c000,0xbff53ec8,0x3fe23ffb,0x3f153ffb,0x3f71bec8,
0x3fe2bf44,0xbf153f44,0xbf71bfed,0x3ff53fed,0xbfc63f8e,0xbfffbfd5,0x3fa23fd5,0xbe493f8e,0xbec8c000,0xbfd5c000,0xbffb0000,0xbf8e0000,
0x3f8e3fed,0x3ec8bf44,0x3fd5bf44,0xbffbbfed,0xbfd5bfb5,0x3ffb3fb5,0xbf8e3fb5,0xbec8bfb5,0x3ffb3f44,0x3f8e3fed,0x3ec8bfed,0x3fd53f44,
0xbff50000,0xbf710000,0x3f154000,0x3fe24000,0x3fa2bf8e,0xbfffbfd5,0xbfc6bfd5,0x3e493f8e,0xbe493fed,0xbfa2bfed,0x3fff3f44,0xbfc6bf44,
0xbf71bffb,0x3f15bec8,0xbfe23ec8,0xbff5bffb,0x3f444000,0x3fed4000,0x3fed0000,0x3f440000,0xbfedbfb5,0x3f443fb5,0xbf443fb5,0x3fed3fb5,
0x3fed0000,0xbf440000,0xbf44c000,0x3fed4000,0xbf443fb5,0xbfedbfb5,0x3fed3fb5,0x3f443fb5,0x3fe20000,0x3f150000,0xbf71c000,0xbff5c000,
0xbe493fd5,0x3fc63f8e,0x3fff3f8e,0xbfa2bfd5,0xbfc6bfed,0x3fff3fed,0xbfa23f44,0xbe49bf44,0x3ff53ec8,0x3fe23ffb,0xbf15bffb,0x3f713ec8,
0xbf8ec000,0xbffbc000,0xbfd50000,0xbec80000,0x3ffb3f44,0xbfd5bfed,0xbec8bfed,0xbf8ebf44,0xbec83fb5,0xbf8ebfb5,0x3ffb3fb5,0xbfd5bfb5,
0xbfd5bfed,0xbec8bf44,0xbf8e3f44,0xbffbbfed,0xbfc60000,0xbe490000,0x3fa24000,0x3fff4000,0xbf71bffb,0xbf15bec8,0xbfe2bec8,0x3ff53ffb,
0x3ff53f44,0xbf71bf44,0xbf15bfed,0x3fe23fed,0x3e493fd5,0xbfa2bf8e,0x3fff3f8e,0x3fc63fd5,0x40004000,0x3fb54000,0x0,0xbfb50000,
0x40004000,0xbfb50000,0x0,0xbfb5c000,0x40004000,0xbfb5c000,0x0,0x3fb50000,0x40004000,0x3fb50000,0x0,0x3fb54000,
0xbfc6bfb5,0xbfffbfb5,0xbfa2bfb5,0x3e49bfb5,0xbfe2bfd5,0x3f15bf8e,0xbf71bf8e,0x3ff53fd5,0xbff5bfed,0x3fe23fed,0xbf15bf44,0xbf713f44,
0xbfffbffb,0xbfa23ec8,0xbe49bec8,0xbfc6bffb,0x3ec80000,0x3fd50000,0x3ffb4000,0x3f8e4000,0x3f8e3f44,0x3ec83fed,0x3fd53fed,0xbffbbf44,
0x3fd53fb5,0xbffbbfb5,0x3f8e3fb5,0x3ec8bfb5,0x3ffb3fed,0x3f8ebf44,0x3ec83f44,0x3fd53fed,0x3f713fb5,0xbf153fb5,0xbfe2bfb5,0xbff5bfb5,
0xbe493ec8,0xbfa2bffb,0xbfffbffb,0x3fc6bec8,0xbfa2bf44,0x3fff3f44,0xbfc6bfed,0x3e493fed,0xbff5bfd5,0xbf713f8e,0xbf15bf8e,0xbfe2bfd5,
0xbfedc000,0xbf44c000,0x3f440000,0x3fed0000,0xbf44bfb5,0x3fed3fb5,0x3fed3fb5,0xbf443fb5,0x3f440000,0xbfed0000,0x3fed4000,0xbf44c000,
0x3fed3fb5,0x3f44bfb5,0x3f443fb5,0x3fed3fb5,0x3ff53fb5,0x3fe23fb5,0x3f153fb5,0xbf713fb5,0x3fc63ffb,0xbfffbec8,0xbfa2bec8,0xbe49bffb,
0xbe493f44,0x3fc6bf44,0xbfffbfed,0x3fa23fed,0xbfe2bf8e,0xbf153fd5,0xbf71bfd5,0xbff5bf8e,0xbf8e0000,0xbffb0000,0xbfd5c000,0xbec8c000,
0xbffbbfed,0x3fd5bf44,0x3ec8bf44,0x3f8e3fed,0xbec8bfb5,0xbf8e3fb5,0x3ffb3fb5,0xbfd5bfb5,0x3fd53f44,0x3ec8bfed,0x3f8e3fed,0x3ffb3f44,
0xbe49bfb5,0x3fa2bfb5,0x3fff3fb5,0x3fc63fb5,0x3ff53f8e,0xbf713fd5,0x3f153fd5,0xbfe2bf8e,0x3f713fed,0x3f15bfed,0xbfe2bf44,0x3ff53f44,
0xbfc6bec8,0xbe493ffb,0xbfa2bffb,0xbfffbec8,0x4000,0xbfb54000,0xc0000000,0xbfb50000,0xc000,0x3fb50000,0x40000000,0xbfb54000,
0x4000,0x3fb5c000,0xc0000000,0x3fb50000,0xc000,0xbfb50000,0x40000000,0x3fb5c000,0xbfa2bfb5,0x3e49bfb5,0x3fc6bfb5,0x3fffbfb5,
0x3f713fd5,0xbff53f8e,0xbfe23f8e,0x3f15bfd5,0xbf15bfed,0xbf713fed,0x3ff5bf44,0xbfe23f44,0x3e493ffb,0x3fc6bec8,0xbfff3ec8,0xbfa23ffb,
0x3ffb0000,0x3f8e0000,0xbec84000,0xbfd54000,0xbfd5bf44,0x3ffbbfed,0x3f8ebfed,0x3ec83f44,0x3f8e3fb5,0x3ec8bfb5,0xbfd53fb5,0x3ffbbfb5,
0xbec8bfed,0xbfd53f44,0x3ffbbf44,0x3f8ebfed,0xbfe23fb5,0xbff53fb5,0xbf71bfb5,0x3f15bfb5,0x3fffbec8,0xbfc63ffb,0xbe493ffb,0xbfa23ec8,
0xbfc6bf44,0x3e493f44,0x3fa2bfed,0xbfff3fed,0x3f153fd5,0x3fe2bf8e,0xbff53f8e,0xbf713fd5,0x3f44c000,0x3fedc000,0x3fed0000,0x3f440000,
0xbfed3fb5,0x3f44bfb5,0xbf44bfb5,0x3fedbfb5,0x3fed0000,0xbf440000,0xbf444000,0x3fedc000,0xbf44bfb5,0xbfed3fb5,0x3fedbfb5,0x3f44bfb5,
0x3f153fb5,0xbf713fb5,0xbff53fb5,0xbfe23fb5,0x3fa2bffb,0x3e493ec8,0x3fc63ec8,0xbfff3ffb,0xbfff3f44,0x3fa2bf44,0x3e49bfed,0xbfc63fed,
0x3f713f8e,0x3ff5bfd5,0xbfe23fd5,0xbf153f8e,0xbfd50000,0xbec80000,0x3f8ec000,0x3ffbc000,0xbec83fed,0xbf8e3f44,0xbffb3f44,0x3fd5bfed,
0x3ffbbfb5,0xbfd53fb5,0x3ec83fb5,0x3f8ebfb5,0xbf8ebf44,0xbffb3fed,0x3fd5bfed,0x3ec8bf44,0x3fffbfb5,0x3fc6bfb5,0x3e493fb5,0xbfa23fb5,
0xbf15bf8e,0x3fe2bfd5,0x3ff5bfd5,0xbf713f8e,0xbfe23fed,0x3ff5bfed,0xbf71bf44,0xbf153f44,0x3fa23ec8,0x3fffbffb,0xbfc63ffb,0xbe493ec8,
0xc0004000,0xbfb54000,0x0,0x3fb50000,0xc0004000,0x3fb50000,0x0,0x3fb5c000,0xc0004000,0x3fb5c000,0x0,0xbfb50000,
0xc0004000,0xbfb50000,0x0,0xbfb54000,0x3fc6bfb5,0x3fffbfb5,0x3fa2bfb5,0xbe49bfb5,0x3fe2bfd5,0xbf15bf8e,0x3f71bf8e,0xbff53fd5,
0x3ff5bfed,0xbfe23fed,0x3f15bf44,0x3f713f44,0x3fffbffb,0x3fa23ec8,0x3e49bec8,0x3fc6bffb,0xbec80000,0xbfd50000,0xbffb4000,0xbf8e4000,
0xbf8e3f44,0xbec83fed,0xbfd53fed,0x3ffbbf44,0xbfd53fb5,0x3ffbbfb5,0xbf8e3fb5,0xbec8bfb5,0xbffb3fed,0xbf8ebf44,0xbec83f44,0xbfd53fed,
0xbf713fb5,0x3f153fb5,0x3fe2bfb5,0x3ff5bfb5,0x3e493ec8,0x3fa2bffb,0x3fffbffb,0xbfc6bec8,0x3fa2bf44,0xbfff3f44,0x3fc6bfed,0xbe493fed,
0x3ff5bfd5,0x3f713f8e,0x3f15bf8e,0x3fe2bfd5,0x3fedc000,0x3f44c000,0xbf440000,0xbfed0000,0x3f44bfb5,0xbfed3fb5,0xbfed3fb5,0x3f443fb5,
0xbf440000,0x3fed0000,0xbfed4000,0x3f44c000,0xbfed3fb5,0xbf44bfb5,0xbf443fb5,0xbfed3fb5,0xbff53fb5,0xbfe23fb5,0xbf153fb5,0x3f713fb5,
0xbfc63ffb,0x3fffbec8,0x3fa2bec8,0x3e49bffb,0x3e493f44,0xbfc6bf44,0x3fffbfed,0xbfa23fed,0x3fe2bf8e,0x3f153fd5,0x3f71bfd5,0x3ff5bf8e,
0x3f8e0000,0x3ffb0000,0x3fd5c000,0x3ec8c000,0x3ffbbfed,0xbfd5bf44,0xbec8bf44,0xbf8e3fed,0x3ec8bfb5,0x3f8e3fb5,0xbffb3fb5,0x3fd5bfb5,
0xbfd53f44,0xbec8bfed,0xbf8e3fed,0xbffb3f44,0x3e49bfb5,0xbfa2bfb5,0xbfff3fb5,0xbfc63fb5,0xbff53f8e,0x3f713fd5,0xbf153fd5,0x3fe2bf8e,
0xbf713fed,0xbf15bfed,0x3fe2bf44,0xbff53f44,0x3fc6bec8,0x3e493ffb,0x3fa2bffb,0x3fffbec8,0x4000,0x3fb54000,0x40000000,0x3fb50000,
0xc000,0xbfb50000,0xc0000000,0x3fb54000,0x4000,0xbfb5c000,0x40000000,0xbfb50000,0xc000,0x3fb50000,0xc0000000,0xbfb5c000,
0x3fa2bfb5,0xbe49bfb5,0xbfc6bfb5,0xbfffbfb5,0xbf713fd5,0x3ff53f8e,0x3fe23f8e,0xbf15bfd5,0x3f15bfed,0x3f713fed,0xbff5bf44,0x3fe23f44,
0xbe493ffb,0xbfc6bec8,0x3fff3ec8,0x3fa23ffb,0xbffb0000,0xbf8e0000,0x3ec84000,0x3fd54000,0x3fd5bf44,0xbffbbfed,0xbf8ebfed,0xbec83f44,
0xbf8e3fb5,0xbec8bfb5,0x3fd53fb5,0xbffbbfb5,0x3ec8bfed,0x3fd53f44,0xbffbbf44,0xbf8ebfed,0x3fe23fb5,0x3ff53fb5,0x3f71bfb5,0xbf15bfb5,
0xbfffbec8,0x3fc63ffb,0x3e493ffb,0x3fa23ec8,0x3fc6bf44,0xbe493f44,0xbfa2bfed,0x3fff3fed,0xbf153fd5,0xbfe2bf8e,0x3ff53f8e,0x3f713fd5,
0xbf44c000,0xbfedc000,0xbfed0000,0xbf440000,0x3fed3fb5,0xbf44bfb5,0x3f44bfb5,0xbfedbfb5,0xbfed0000,0x3f440000,0x3f444000,0xbfedc000,
0x3f44bfb5,0x3fed3fb5,0xbfedbfb5,0xbf44bfb5,0xbf153fb5,0x3f713fb5,0x3ff53fb5,0x3fe23fb5,0xbfa2bffb,0xbe493ec8,0xbfc63ec8,0x3fff3ffb,
0x3fff3f44,0xbfa2bf44,0xbe49bfed,0x3fc63fed,0xbf713f8e,0xbff5bfd5,0x3fe23fd5,0x3f153f8e,0x3fd50000,0x3ec80000,0xbf8ec000,0xbffbc000,
0x3ec83fed,0x3f8e3f44,0x3ffb3f44,0xbfd5bfed,0xbffbbfb5,0x3fd53fb5,0xbec83fb5,0xbf8ebfb5,0x3f8ebf44,0x3ffb3fed,0xbfd5bfed,0xbec8bf44,
0xbfffbfb5,0xbfc6bfb5,0xbe493fb5,0x3fa23fb5,0x3f15bf8e,0xbfe2bfd5,0xbff5bfd5,0x3f713f8e,0x3fe23fed,0xbff5bfed,0x3f71bf44,0x3f153f44,
0xbfa23ec8,0xbfffbffb,0x3fc63ffb,0x3e493ec8,0x80003f80,0x3f800000,0x80003f80,0x3f800000,0x80003f80,0x3f800000,0x80003f80,0x3f800000,
0x80003f80,0x3f800000,0x80003f80,0x3f800000,0x80003f80,0x3f800000,0x80003f80,0x3f800000,0x80003f80,0x3f800000,0x8000bf80,0xbf800000,
0x3f353f35,0x3f35bf35,0xbf35bf35,0xbf353f35,0x3f800000,0xbf80,0xbf800000,0x3f80,0x3f35bf35,0xbf35bf35,0xbf353f35,0x3f353f35,
0x80003f80,0x3f800000,0x80003f80,0x3f800000,0x3f800000,0xbf80,0x3f800000,0xbf80,0x8000bf80,0xbf800000,0x8000bf80,0xbf800000,
0xbf800000,0x3f80,0xbf800000,0x3f80,0x80003f80,0x3f800000,0x8000bf80,0xbf800000,0x3f35bf35,0xbf35bf35,0xbf353f35,0x3f353f35,
0xbf800000,0x3f80,0x3f800000,0xbf80,0x3f353f35,0x3f35bf35,0xbf35bf35,0xbf353f35,0x80003f80,0x3f800000,0x80003f80,0x3f800000,
0x8000bf80,0xbf800000,0x8000bf80,0xbf800000,0x80003f80,0x3f800000,0x80003f80,0x3f800000,0x8000bf80,0xbf800000,0x8000bf80,0xbf800000,
0x80003f80,0x3f800000,0x8000bf80,0xbf800000,0xbf35bf35,0xbf353f35,0x3f353f35,0x3f35bf35,0x3f800000,0xbf80,0xbf800000,0x3f80,
0xbf353f35,0x3f353f35,0x3f35bf35,0xbf35bf35,0x80003f80,0x3f800000,0x80003f80,0x3f800000,0xbf800000,0x3f80,0xbf800000,0x3f80,
0x8000bf80,0xbf800000,0x8000bf80,0xbf800000,0x3f800000,0xbf80,0x3f800000,0xbf80,0x80003f80,0x3f800000,0x8000bf80,0xbf800000,
0xbf353f35,0x3f353f35,0x3f35bf35,0xbf35bf35,0xbf800000,0x3f80,0x3f800000,0xbf80,0xbf35bf35,0xbf353f35,0x3f353f35,0x3f35bf35,
0x3f803f80,0x80008000,0x80008000,0xbf80bf80,0x3f803f80,0x80008000,0x80008000,0xbf80bf80,0x3f803f80,0x80008000,0x80008000,0xbf80bf80,
0x3f803f80,0x80008000,0x80008000,0xbf80bf80,0x3f353f80,0x3f358000,0x3f358000,0xbf35bf80,0xbf350000,0x3f353f80,0x3f353f80,0x3f358000,
0xbf35bf80,0xbf358000,0xbf358000,0x3f353f80,0x3f350000,0xbf35bf80,0xbf35bf80,0xbf358000,0x3f80,0x3f808000,0x3f808000,0x8000bf80,
0xbf80,0xbf808000,0xbf808000,0x80003f80,0x3f80,0x3f808000,0x3f808000,0x8000bf80,0xbf80,0xbf808000,0xbf808000,0x80003f80,
0xbf353f80,0x3f358000,0x3f358000,0x3f35bf80,0x3f350000,0x3f35bf80,0x3f35bf80,0xbf358000,0x3f35bf80,0xbf358000,0xbf358000,0xbf353f80,
0xbf350000,0xbf353f80,0xbf353f80,0x3f358000,0xbf803f80,0x80008000,0x80008000,0x3f80bf80,0xbf803f80,0x80008000,0x80008000,0x3f80bf80,
0xbf803f80,0x80008000,0x80008000,0x3f80bf80,0xbf803f80,0x80008000,0x80008000,0x3f80bf80,0xbf353f80,0xbf358000,0xbf358000,0x3f35bf80,
0x3f350000,0xbf353f80,0xbf353f80,0xbf358000,0x3f35bf80,0x3f358000,0x3f358000,0xbf353f80,0xbf350000,0x3f35bf80,0x3f35bf80,0x3f358000,
0x3f80,0xbf808000,0xbf808000,0x8000bf80,0xbf80,0x3f808000,0x3f808000,0x80003f80,0x3f80,0xbf808000,0xbf808000,0x8000bf80,
0xbf80,0x3f808000,0x3f808000,0x80003f80,0x3f353f80,0xbf358000,0xbf358000,0xbf35bf80,0xbf350000,0xbf35bf80,0xbf35bf80,0x3f358000,
0xbf35bf80,0x3f358000,0x3f358000,0x3f353f80,0x3f350000,0x3f353f80,0x3f353f80,0xbf358000,0x3f800000,0x0,0x3f800000,0x0,
0x3f800000,0x0,0x3f800000,0x0,0x3f800000,0x0,0x3f800000,0x0,0x3f800000,0x0,0x3f800000,0x0,
0x3f800000,0x0,0x3f7fb10f,0xbd48fb30,0x3f7ec46d,0xbdc8bd36,0x3f7d3aac,0xbe164083,0x3f7b14be,0xbe47c5c2,0x3f7853f8,0xbe78cfcc,
0x3f74fa0b,0xbe94a031,0x3f710908,0xbeac7cd4,0x3f800000,0x0,0x3f7ec46d,0xbdc8bd36,0x3f7b14be,0xbe47c5c2,0x3f74fa0b,0xbe94a031,
0x3f6c835e,0xbec3ef15,0x3f61c598,0xbef15aea,0x3f54db31,0xbf0e39da,0x3f45e403,0xbf226799,0x3f800000,0x0,0x3f7d3aac,0xbe164083,
0x3f74fa0b,0xbe94a031,0x3f676bd8,0xbedae880,0x3f54db31,0xbf0e39da,0x3f3daef9,0xbf2beb4a,0x3f226799,0xbf45e403,0x3f039c3d,0xbf5b941a,
0x3f800000,0x0,0x3f7b14be,0xbe47c5c2,0x3f6c835e,0xbec3ef15,0x3f54db31,0xbf0e39da,0x3f3504f3,0xbf3504f3,0x3f0e39da,0xbf54db31,
0x3ec3ef15,0xbf6c835e,0x3e47c5c2,0xbf7b14be,0x3f800000,0x0,0x3f7853f8,0xbe78cfcc,0x3f61c598,0xbef15aea,0x3f3daef9,0xbf2beb4a,
0x3f0e39da,0xbf54db31,0x3eac7cd4,0xbf710908,0x3dc8bd36,0xbf7ec46d,0xbe164083,0xbf7d3aac,0x3f800000,0x0,0x3f74fa0b,0xbe94a031,
0x3f54db31,0xbf0e39da,0x3f226799,0xbf45e403,0x3ec3ef15,0xbf6c835e,0x3dc8bd36,0xbf7ec46d,0xbe47c5c2,0xbf7b14be,0xbef15aea,0xbf61c598,
0x3f800000,0x0,0x3f710908,0xbeac7cd4,0x3f45e403,0xbf226799,0x3f039c3d,0xbf5b941a,0x3e47c5c2,0xbf7b14be,0xbe164083,0xbf7d3aac,
0xbef15aea,0xbf61c598,0xbf3daef9,0xbf2beb4a,0x3f800000,0x0,0x3f800000,0x0,0x3f800000,0x0,0x3f800000,0x0,
0x3f800000,0x0,0x3f800000,0x0,0x3f800000,0x0,0x3f800000,0x0,0x3f6c835e,0xbec3ef15,0x3f676bd8,0xbedae880,
0x3f61c598,0xbef15aea,0x3f5b941a,0xbf039c3d,0x3f54db31,0xbf0e39da,0x3f4d9f02,0xbf187fc0,0x3f45e403,0xbf226799,0x3f3daef9,0xbf2beb4a,
0x3f3504f3,0xbf3504f3,0x3f226799,0xbf45e403,0x3f0e39da,0xbf54db31,0x3ef15aea,0xbf61c598,0x3ec3ef15,0xbf6c835e,0x3e94a031,0xbf74fa0b,
0x3e47c5c2,0xbf7b14be,0x3dc8bd36,0xbf7ec46d,0x3ec3ef15,0xbf6c835e,0x3e78cfcc,0xbf7853f8,0x3dc8bd36,0xbf7ec46d,0xbd48fb30,0xbf7fb10f,
0xbe47c5c2,0xbf7b14be,0xbeac7cd4,0xbf710908,0xbef15aea,0xbf61c598,0xbf187fc0,0xbf4d9f02,0x0,0xbf800000,0xbe47c5c2,0xbf7b14be,
0xbec3ef15,0xbf6c835e,0xbf0e39da,0xbf54db31,0xbf3504f3,0xbf3504f3,0xbf54db31,0xbf0e39da,0xbf6c835e,0xbec3ef15,0xbf7b14be,0xbe47c5c2,
0xbec3ef15,0xbf6c835e,0xbf187fc0,0xbf4d9f02,0xbf45e403,0xbf226799,0xbf676bd8,0xbedae880,0xbf7b14be,0xbe47c5c2,0xbf7fb10f,0x3d48fb30,
0xbf74fa0b,0x3e94a031,0xbf5b941a,0x3f039c3d,0xbf3504f3,0xbf3504f3,0xbf61c598,0xbef15aea,0xbf7b14be,0xbe47c5c2,0xbf7ec46d,0x3dc8bd36,
0xbf6c835e,0x3ec3ef15,0xbf45e403,0x3f226799,0xbf0e39da,0x3f54db31,0xbe94a031,0x3f74fa0b,0xbf6c835e,0xbec3ef15,0xbf7fb10f,0xbd48fb30,
0xbf74fa0b,0x3e94a031,0xbf4d9f02,0x3f187fc0,0xbf0e39da,0x3f54db31,0xbe78cfcc,0x3f7853f8,0x3dc8bd36,0x3f7ec46d,0x3edae880,0x3f676bd8,
0x80003f80,0x3f800000,0x3f800000,0xbf80,0x3ec43f6d,0x3f6dbec4,0x3f6dbec4,0xbec4bf6d,0x3f353f35,0x3f35bf35,0x3f35bf35,0xbf35bf35,
0x3f6d3ec4,0x3ec4bf6d,0x3ec4bf6d,0xbf6dbec4,0x80003f80,0x3f800000,0xbf800000,0x3f80,0x3f6d3ec4,0x3ec4bf6d,0xbec43f6d,0x3f6d3ec4,
0x3f35bf35,0xbf35bf35,0x3f353f35,0x3f35bf35,0xbec4bf6d,0xbf6d3ec4,0x3f6dbec4,0xbec4bf6d,0x80003f80,0x3f800000,0x3f800000,0xbf80,
0x3f6dbec4,0xbec4bf6d,0xbec4bf6d,0xbf6d3ec4,0xbf35bf35,0xbf353f35,0xbf353f35,0x3f353f35,0xbec43f6d,0x3f6d3ec4,0x3f6d3ec4,0x3ec4bf6d,
0x80003f80,0x3f800000,0xbf800000,0x3f80,0x3ec4bf6d,0xbf6dbec4,0x3f6d3ec4,0x3ec4bf6d,0xbf353f35,0x3f353f35,0xbf35bf35,0xbf353f35,
0x3f6dbec4,0xbec4bf6d,0x3ec43f6d,0x3f6dbec4,0x80003f80,0x3f800000,0x3f800000,0xbf80,0xbec4bf6d,0xbf6d3ec4,0xbf6d3ec4,0x3ec43f6d,
0x3f353f35,0x3f35bf35,0x3f35bf35,0xbf35bf35,0xbf6dbec4,0xbec43f6d,0xbec43f6d,0x3f6d3ec4,0x80003f80,0x3f800000,0xbf800000,0x3f80,
0xbf6dbec4,0xbec43f6d,0x3ec4bf6d,0xbf6dbec4,0x3f35bf35,0xbf35bf35,0x3f353f35,0x3f35bf35,0x3ec43f6d,0x3f6dbec4,0xbf6d3ec4,0x3ec43f6d,
0x80003f80,0x3f800000,0x3f800000,0xbf80,0xbf6d3ec4,0x3ec43f6d,0x3ec43f6d,0x3f6dbec4,0xbf35bf35,0xbf353f35,0xbf353f35,0x3f353f35,
0x3ec4bf6d,0xbf6dbec4,0xbf6dbec4,0xbec43f6d,0x80003f80,0x3f800000,0xbf800000,0x3f80,0xbec43f6d,0x3f6d3ec4,0xbf6dbec4,0xbec43f6d,
0xbf353f35,0x3f353f35,0xbf35bf35,0xbf353f35,0xbf6d3ec4,0x3ec43f6d,0xbec4bf6d,0xbf6d3ec4,0x3f803f80,0x80008000,0x80008000,0xbf80bf80,
0x3f803f80,0x80008000,0x80008000,0xbf80bf80,0x3f803f80,0x80008000,0x80008000,0xbf80bf80,0x3f803f80,0x80008000,0x80008000,0xbf80bf80,
0x3ec43f6d,0x3f6d3ec4,0x3f6d3ec4,0xbec4bf6d,0xbf6dbec4,0x3ec43f6d,0x3ec43f6d,0x3f6d3ec4,0xbec4bf6d,0xbf6dbec4,0xbf6dbec4,0x3ec43f6d,
0x3f6d3ec4,0xbec4bf6d,0xbec4bf6d,0xbf6dbec4,0xbf353f35,0x3f353f35,0x3f353f35,0x3f35bf35,0x3f35bf35,0xbf35bf35,0xbf35bf35,0xbf353f35,
0xbf353f35,0x3f353f35,0x3f353f35,0x3f35bf35,0x3f35bf35,0xbf35bf35,0xbf35bf35,0xbf353f35,0xbf6d3ec4,0xbec43f6d,0xbec43f6d,0x3f6dbec4,
0xbec43f6d,0x3f6dbec4,0x3f6dbec4,0x3ec4bf6d,0x3f6dbec4,0x3ec4bf6d,0x3ec4bf6d,0xbf6d3ec4,0x3ec4bf6d,0xbf6d3ec4,0xbf6d3ec4,0xbec43f6d,
0x0,0xbf803f80,0xbf803f80,0x80008000,0x0,0xbf803f80,0xbf803f80,0x80008000,0x0,0xbf803f80,0xbf803f80,0x80008000,
0x0,0xbf803f80,0xbf803f80,0x80008000,0x3f6dbec4,0xbec43f6d,0xbec43f6d,0xbf6d3ec4,0x3ec4bf6d,0x3f6dbec4,0x3f6dbec4,0xbec43f6d,
0xbf6d3ec4,0x3ec4bf6d,0x3ec4bf6d,0x3f6dbec4,0xbec43f6d,0xbf6d3ec4,0xbf6d3ec4,0x3ec4bf6d,0x3f35bf35,0x3f353f35,0x3f353f35,0xbf353f35,
0xbf353f35,0xbf35bf35,0xbf35bf35,0x3f35bf35,0x3f35bf35,0x3f353f35,0x3f353f35,0xbf353f35,0xbf353f35,0xbf35bf35,0xbf35bf35,0x3f35bf35,
0xbec4bf6d,0x3f6d3ec4,0x3f6d3ec4,0x3ec43f6d,0x3f6d3ec4,0x3ec43f6d,0x3ec43f6d,0xbf6dbec4,0x3ec43f6d,0xbf6dbec4,0xbf6dbec4,0xbec4bf6d,
0xbf6dbec4,0xbec4bf6d,0xbec4bf6d,0x3f6d3ec4,0x3f800000,0x0,0x3f7fec43,0xbcc90ab0,0x3f7fb10f,0xbd48fb30,0x3f7f4e6d,0xbd96a905,
0x3f7ec46d,0xbdc8bd36,0x3f7e1324,0xbdfab273,0x3f7d3aac,0xbe164083,0x3f7c3b28,0xbe2f10a2,0x3f800000,0x0,0x3f7f4e6d,0xbd96a905,
0x3f7d3aac,0xbe164083,0x3f79c79d,0xbe605c13,0x3f74fa0b,0xbe94a031,0x3f6ed89e,0xbeb8442a,0x3f676bd8,0xbedae880,0x3f5ebe05,0xbefc5d27,
0x3f800000,0x0,0x3f7e1324,0xbdfab273,0x3f7853f8,0xbe78cfcc,0x3f6ed89e,0xbeb8442a,0x3f61c598,0xbef15aea,0x3f514d3d,0xbf13682a,
0x3f3daef9,0xbf2beb4a,0x3f273656,0xbf41d870,0x3f800000,0x0,0x3f7c3b28,0xbe2f10a2,0x3f710908,0xbeac7cd4,0x3f5ebe05,0xbefc5d27,
0x3f45e403,0xbf226799,0x3f273656,0xbf41d870,0x3f039c3d,0xbf5b941a,0x3eb8442a,0xbf6ed89e,0x3f800000,0x0,0x3f79c79d,0xbe605c13,
0x3f676bd8,0xbedae880,0x3f49d112,0xbf1d7fd1,0x3f226799,0xbf45e403,0x3ee63375,0xbf64aa59,0x3e78cfcc,0xbf7853f8,0x3cc90ab0,0xbf7fec43,
0x3f800000,0x0,0x3f76ba07,0xbe888e93,0x3f5b941a,0xbf039c3d,0x3f3085bb,0xbf396842,0x3ef15aea,0xbf61c598,0x3e605c13,0xbf79c79d,
0xbd48fb30,0xbf7fb10f,0xbea09ae5,0xbf731447,0x3f800000,0x0,0x3f731447,0xbea09ae5,0x3f4d9f02,0xbf187fc0,0x3f13682a,0xbf514d3d,
0x3e94a031,0xbf74fa0b,0xbcc90ab0,0xbf7fec43,0xbeac7cd4,0xbf710908,0xbf1d7fd1,0xbf49d112,0x3f800000,0x0,0x3f6ed89e,0xbeb8442a,
0x3f3daef9,0xbf2beb4a,0x3ee63375,0xbf64aa59,0x3dc8bd36,0xbf7ec46d,0xbe888e93,0xbf76ba07,0xbf187fc0,0xbf4d9f02,0xbf584853,0xbf08f59b,
0x3f7b14be,0xbe47c5c2,0x3f79c79d,0xbe605c13,0x3f7853f8,0xbe78cfcc,0x3f76ba07,0xbe888e93,0x3f74fa0b,0xbe94a031,0x3f731447,0xbea09ae5,
0x3f710908,0xbeac7cd4,0x3f6ed89e,0xbeb8442a,0x3f54db31,0xbf0e39da,0x3f49d112,0xbf1d7fd1,0x3f3daef9,0xbf2beb4a,0x3f3085bb,0xbf396842,
0x3f226799,0xbf45e403,0x3f13682a,0xbf514d3d,0x3f039c3d,0xbf5b941a,0x3ee63375,0xbf64aa59,0x3f0e39da,0xbf54db31,0x3ee63375,0xbf64aa59,
0x3eac7cd4,0xbf710908,0x3e605c13,0xbf79c79d,0x3dc8bd36,0xbf7ec46d,0xbcc90ab0,0xbf7fec43,0xbe164083,0xbf7d3aac,0xbe888e93,0xbf76ba07,
0x3e47c5c2,0xbf7b14be,0x3cc90ab0,0xbf7fec43,0xbe164083,0xbf7d3aac,0xbea09ae5,0xbf731447,0xbef15aea,0xbf61c598,0xbf1d7fd1,0xbf49d112,
0xbf3daef9,0xbf2beb4a,0xbf584853,0xbf08f59b,0xbe47c5c2,0xbf7b14be,0xbecf7bca,0xbf6a09a7,0xbf187fc0,0xbf4d9f02,0xbf41d870,0xbf273656,
0xbf61c598,0xbef15aea,0xbf76ba07,0xbe888e93,0xbf7fb10f,0xbd48fb30,0xbf7c3b28,0x3e2f10a2,0xbf0e39da,0xbf54db31,0xbf41d870,0xbf273656,
0xbf676bd8,0xbedae880,0xbf7c3b28,0xbe2f10a2,0xbf7ec46d,0x3dc8bd36,0xbf6ed89e,0x3eb8442a,0xbf4d9f02,0x3f187fc0,0xbf1d7fd1,0x3f49d112,
0xbf54db31,0xbf0e39da,0xbf76ba07,0xbe888e93,0xbf7fb10f,0x3d48fb30,0xbf6ed89e,0x3eb8442a,0xbf45e403,0x3f226799,0xbf08f59b,0x3f584853,
0xbe78cfcc,0x3f7853f8,0x3d96a905,0x3f7f4e6d,0xbf7b14be,0xbe47c5c2,0xbf7c3b28,0x3e2f10a2,0xbf5b941a,0x3f039c3d,0xbf1d7fd1,0x3f49d112,
0xbe94a031,0x3f74fa0b,0x3d96a905,0x3f7f4e6d,0x3edae880,0x3f676bd8,0x3f396842,0x3f3085bb,0x80003f80,0x80003f80,0x80003f80,0x80003f80,
0x80003f80,0x80003f80,0x80003f80,0x80003f80,0x80003f80,0x80003f80,0x80003f80,0x80003f80,0x80003f80,0x80003f80,0x80003f80,0x80003f80,
0x3f800000,0x3f800000,0x3f800000,0x3f800000,0x3f800000,0x3f800000,0x3f800000,0x3f800000,0x3f800000,0x3f800000,0x3f800000,0x3f800000,
0x3f800000,0x3f800000,0x3f800000,0x3f800000,0x80003f80,0x3f353f35,0x80003f80,0x3f353f35,0x3f800000,0x3f35bf35,0x3f800000,0x3f35bf35,
0x8000bf80,0xbf35bf35,0x8000bf80,0xbf35bf35,0xbf800000,0xbf353f35,0xbf800000,0xbf353f35,0x3f800000,0x3f35bf35,0x3f800000,0x3f35bf35,
0xbf80,0xbf35bf35,0xbf80,0xbf35bf35,0xbf800000,0xbf353f35,0xbf800000,0xbf353f35,0x3f80,0x3f353f35,0x3f80,0x3f353f35,
0x80003f80,0x3f800000,0x80003f80,0x3f800000,0x8000bf80,0xbf800000,0x8000bf80,0xbf800000,0x80003f80,0x3f800000,0x80003f80,0x3f800000,
0x8000bf80,0xbf800000,0x8000bf80,0xbf800000,0x3f800000,0xbf80,0x3f800000,0xbf80,0xbf800000,0x3f80,0xbf800000,0x3f80,
0x3f800000,0xbf80,0x3f800000,0xbf80,0xbf800000,0x3f80,0xbf800000,0x3f80,0x80003f80,0x3f35bf35,0x80003f80,0x3f35bf35,
0xbf800000,0x3f353f35,0xbf800000,0x3f353f35,0x8000bf80,0xbf353f35,0x8000bf80,0xbf353f35,0x3f800000,0xbf35bf35,0x3f800000,0xbf35bf35,
0x3f800000,0xbf35bf35,0x3f800000,0xbf35bf35,0x3f80,0x3f35bf35,0x3f80,0x3f35bf35,0xbf800000,0x3f353f35,0xbf800000,0x3f353f35,
0xbf80,0xbf353f35,0xbf80,0xbf353f35,0x80003f80,0x3ec43f6d,0x8000bf80,0xbec4bf6d,0x3f353f35,0x3f6d3ec4,0xbf35bf35,0xbf6dbec4,
0x3f800000,0x3f6dbec4,0xbf800000,0xbf6d3ec4,0x3f35bf35,0x3ec4bf6d,0xbf353f35,0xbec43f6d,0x3f800000,0x3f6dbec4,0xbf800000,0xbf6d3ec4,
0x3f35bf35,0x3ec4bf6d,0xbf353f35,0xbec43f6d,0xbf80,0xbec4bf6d,0x3f80,0x3ec43f6d,0xbf35bf35,0xbf6dbec4,0x3f353f35,0x3f6d3ec4,
0x80003f80,0x3f6d3ec4,0x8000bf80,0xbf6dbec4,0x3f35bf35,0xbec4bf6d,0xbf353f35,0x3ec43f6d,0xbf800000,0xbec43f6d,0x3f800000,0x3ec4bf6d,
0x3f353f35,0x3f6dbec4,0xbf35bf35,0xbf6d3ec4,0x3f800000,0x3ec4bf6d,0xbf800000,0xbec43f6d,0xbf35bf35,0xbf6d3ec4,0x3f353f35,0x3f6dbec4,
0x3f80,0x3f6d3ec4,0xbf80,0xbf6dbec4,0x3f35bf35,0xbec4bf6d,0xbf353f35,0x3ec43f6d,0x80003f80,0x3f6dbec4,0x8000bf80,0xbf6d3ec4,
0xbf35bf35,0xbec43f6d,0x3f353f35,0x3ec4bf6d,0x3f800000,0xbec4bf6d,0xbf800000,0x3ec43f6d,0xbf353f35,0x3f6d3ec4,0x3f35bf35,0xbf6dbec4,
0x3f800000,0xbec4bf6d,0xbf800000,0x3ec43f6d,0xbf353f35,0x3f6d3ec4,0x3f35bf35,0xbf6dbec4,0xbf80,0xbf6d3ec4,0x3f80,0x3f6dbec4,
0x3f353f35,0x3ec4bf6d,0xbf35bf35,0xbec43f6d,0x80003f80,0x3ec4bf6d,0x8000bf80,0xbec43f6d,0xbf353f35,0x3f6dbec4,0x3f35bf35,0xbf6d3ec4,
0xbf800000,0x3f6d3ec4,0x3f800000,0xbf6dbec4,0xbf35bf35,0x3ec43f6d,0x3f353f35,0xbec4bf6d,0x3f800000,0xbf6dbec4,0xbf800000,0x3f6d3ec4,
0x3f353f35,0xbec4bf6d,0xbf35bf35,0x3ec43f6d,0x3f80,0x3ec4bf6d,0xbf80,0xbec43f6d,0xbf353f35,0x3f6dbec4,0x3f35bf35,0xbf6d3ec4,
0x80003f80,0x8000bf80,0x80003f80,0x8000bf80,0x80003f80,0x8000bf80,0x80003f80,0x8000bf80,0x80003f80,0x8000bf80,0x80003f80,0x8000bf80,
0x80003f80,0x8000bf80,0x80003f80,0x8000bf80,0x3f800000,0xbf800000,0x3f800000,0xbf800000,0x3f800000,0xbf800000,0x3f800000,0xbf800000,
0x3f800000,0xbf800000,0x3f800000,0xbf800000,0x3f800000,0xbf800000,0x3f800000,0xbf800000,0x80003f80,0xbf35bf35,0x80003f80,0xbf35bf35,
0x3f800000,0xbf353f35,0x3f800000,0xbf353f35,0x8000bf80,0x3f353f35,0x8000bf80,0x3f353f35,0xbf800000,0x3f35bf35,0xbf800000,0x3f35bf35,
0x3f800000,0xbf353f35,0x3f800000,0xbf353f35,0xbf80,0x3f353f35,0xbf80,0x3f353f35,0xbf800000,0x3f35bf35,0xbf800000,0x3f35bf35,
0x3f80,0xbf35bf35,0x3f80,0xbf35bf35,0x80003f80,0xbf800000,0x80003f80,0xbf800000,0x8000bf80,0x3f800000,0x8000bf80,0x3f800000,
0x80003f80,0xbf800000,0x80003f80,0xbf800000,0x8000bf80,0x3f800000,0x8000bf80,0x3f800000,0x3f800000,0x3f80,0x3f800000,0x3f80,
0xbf800000,0xbf80,0xbf800000,0xbf80,0x3f800000,0x3f80,0x3f800000,0x3f80,0xbf800000,0xbf80,0xbf800000,0xbf80,
0x80003f80,0xbf353f35,0x80003f80,0xbf353f35,0xbf800000,0xbf35bf35,0xbf800000,0xbf35bf35,0x8000bf80,0x3f35bf35,0x8000bf80,0x3f35bf35,
0x3f800000,0x3f353f35,0x3f800000,0x3f353f35,0x3f800000,0x3f353f35,0x3f800000,0x3f353f35,0x3f80,0xbf353f35,0x3f80,0xbf353f35,
0xbf800000,0xbf35bf35,0xbf800000,0xbf35bf35,0xbf80,0x3f35bf35,0xbf80,0x3f35bf35,0x80003f80,0xbec4bf6d,0x8000bf80,0x3ec43f6d,
0x3f353f35,0xbf6dbec4,0xbf35bf35,0x3f6d3ec4,0x3f800000,0xbf6d3ec4,0xbf800000,0x3f6dbec4,0x3f35bf35,0xbec43f6d,0xbf353f35,0x3ec4bf6d,
0x3f800000,0xbf6d3ec4,0xbf800000,0x3f6dbec4,0x3f35bf35,0xbec43f6d,0xbf353f35,0x3ec4bf6d,0xbf80,0x3ec43f6d,0x3f80,0xbec4bf6d,
0xbf35bf35,0x3f6d3ec4,0x3f353f35,0xbf6dbec4,0x80003f80,0xbf6dbec4,0x8000bf80,0x3f6d3ec4,0x3f35bf35,0x3ec43f6d,0xbf353f35,0xbec4bf6d,
0xbf800000,0x3ec4bf6d,0x3f800000,0xbec43f6d,0x3f353f35,0xbf6d3ec4,0xbf35bf35,0x3f6dbec4,0x3f800000,0xbec43f6d,0xbf800000,0x3ec4bf6d,
0xbf35bf35,0x3f6dbec4,0x3f353f35,0xbf6d3ec4,0x3f80,0xbf6dbec4,0xbf80,0x3f6d3ec4,0x3f35bf35,0x3ec43f6d,0xbf353f35,0xbec4bf6d,
0x80003f80,0xbf6d3ec4,0x8000bf80,0x3f6dbec4,0xbf35bf35,0x3ec4bf6d,0x3f353f35,0xbec43f6d,0x3f800000,0x3ec43f6d,0xbf800000,0xbec4bf6d,
0xbf353f35,0xbf6dbec4,0x3f35bf35,0x3f6d3ec4,0x3f800000,0x3ec43f6d,0xbf800000,0xbec4bf6d,0xbf353f35,0xbf6dbec4,0x3f35bf35,0x3f6d3ec4,
0xbf80,0x3f6dbec4,0x3f80,0xbf6d3ec4,0x3f353f35,0xbec43f6d,0xbf35bf35,0x3ec4bf6d,0x80003f80,0xbec43f6d,0x8000bf80,0x3ec4bf6d,
0xbf353f35,0xbf6d3ec4,0x3f35bf35,0x3f6dbec4,0xbf800000,0xbf6dbec4,0x3f800000,0x3f6d3ec4,0xbf35bf35,0xbec4bf6d,0x3f353f35,0x3ec43f6d,
0x3f800000,0x3f6d3ec4,0xbf800000,0xbf6dbec4,0x3f353f35,0x3ec43f6d,0xbf35bf35,0xbec4bf6d,0x3f80,0xbec43f6d,0xbf80,0x3ec4bf6d,
0xbf353f35,0xbf6d3ec4,0x3f35bf35,0x3f6dbec4,
};
constexpr int TB_F = 0, TB_E = 512, TB_P2 = 1024;

enum { C_EP = 0, C_Z1 = 32, C_Z2 = 96, C_H3 = 128, C_U = 160, C_X = 256, C_TOTAL = 512 };
struct Scratch {
  unsigned cnt[C_TOTAL];
  uint32_t moda[8 * 2 * D_];
  uint32_t mod[4 * D_ + 256];
  uint32_t z1[120 * 5120];
  uint32_t z2[128 * 4800];
  uint8_t h3[32 * 18 * 4096];
  uint8_t u[72 * D_ * 128];
};
__device__ __align__(1024) Scratch g_s;

#define PF2 8
#define PF2K 16
#define HOLDA 5
#define GOAT 0
#define HW bulk_commit_wait
#define H3W 0
#define X1K 10
#define PEEK 1
#define H3G 1
#define PFF 2
#ifndef NV1
#define NV1 12
#endif
#ifndef NV2
#define NV2 20
#endif
#define GDEP 0
#define TRK0 50
#define W0N 3
#define TRKC 350
#define NG1 2

#define FAILCNT(k) do {} while (0)
#define CK(k) do {} while (0)
#define CKX(k) do {} while (0)
#define TS(k) do {} while (0)
#define TSC(k) do {} while (0)
struct Maps { CUtensorMap z1, z2[2], w1a, w1b, h3[2], w2, wf[4], wm; };
struct Params {
  const __nv_bfloat16 *x, *c, *wmod;
  Scratch* s;
  const uint4* tab;
  const __nv_bfloat16 *wr, *wi, *w1, *w2, *b1, *b2;
  uint32_t* out;
};

__device__ __forceinline__ uint32_t smem_u32(const void* p) { return (uint32_t)__cvta_generic_to_shared(p); }
__device__ __forceinline__ void mbar_init(uint32_t b, int c) { asm volatile("mbarrier.init.shared::cta.b64 [%0], %1;" ::"r"(b), "r"(c)); }
__device__ __forceinline__ void mbar_expect(uint32_t b, int bytes) { asm volatile("mbarrier.arrive.expect_tx.shared::cta.b64 _, [%0], %1;" ::"r"(b), "r"(bytes) : "memory"); }
__device__ __forceinline__ void mbar_arrive(uint32_t b) { asm volatile("mbarrier.arrive.shared::cta.b64 _, [%0];" ::"r"(b) : "memory"); }
#define MBAR_WAIT(SEM)                                                                                                         \
  asm volatile("{\n.reg .pred p;\n.reg .u32 it;\nmov.u32 it, 0;\nW:\nmbarrier.try_wait.parity" SEM ".shared::cta.b64 p, [%0], %1;\n" \
               "@p bra.uni D;\nadd.u32 it, it, 1;\nsetp.lt.u32 p, it, 0x400000;\n@p bra.uni W;\ntrap;\nD:\n}" ::"r"(b), "r"(ph) : "memory")
__device__ __forceinline__ void mbar_wait(uint32_t b, int ph) { MBAR_WAIT(""); }
__device__ __forceinline__ uint32_t mbar_test(uint32_t b, int ph) {
  uint32_t ok;
  asm volatile("{\n.reg .pred p;\nmbarrier.test_wait.parity.shared::cta.b64 p, [%1], %2;\nselp.u32 %0, 1, 0, p;\n}\n" : "=r"(ok) : "r"(b), "r"(ph) : "memory");
  return ok;
}
__device__ __forceinline__ void tma2d(uint32_t dst, const CUtensorMap* m, int c0, int c1, uint32_t bar) {
  asm volatile("cp.async.bulk.tensor.2d.shared::cluster.global.mbarrier::complete_tx::bytes [%0], [%1, {%3, %4}], [%2];" ::"r"(dst), "l"(m), "r"(bar), "r"(c0), "r"(c1) : "memory");
}
__device__ __forceinline__ uint64_t pol_ef() { uint64_t p; asm("createpolicy.fractional.L2::evict_first.b64 %0, 1.0;" : "=l"(p)); return p; }
__device__ __forceinline__ void tma3d_ef(uint32_t dst, const CUtensorMap* m, int c1, int c2, uint32_t bar) {
  asm volatile("cp.async.bulk.tensor.3d.shared::cluster.global.mbarrier::complete_tx::bytes.L2::cache_hint [%0], [%1, {%3, %4, %5}], [%2], %6;" ::"r"(dst), "l"(m), "r"(bar), "r"(0), "r"(c1), "r"(c2), "l"(pol_ef()) : "memory");
}
__device__ __forceinline__ void tma4d_ef(uint32_t dst, const CUtensorMap* m, int c1, int c2, int c3, uint32_t bar) {
  asm volatile("cp.async.bulk.tensor.4d.shared::cluster.global.mbarrier::complete_tx::bytes.L2::cache_hint [%0], [%1, {%3, %7, %4, %5}], [%2], %6;" ::"r"(dst), "l"(m), "r"(bar), "r"(0), "r"(c2), "r"(c3), "l"(pol_ef()), "r"(c1) : "memory");
}
__device__ __forceinline__ void bulk_ld(uint32_t dst, const void* src, int bytes, uint32_t bar) {
  asm volatile("cp.async.bulk.shared::cluster.global.mbarrier::complete_tx::bytes [%0], [%1], %2, [%3];" ::"r"(dst), "l"(src), "r"(bytes), "r"(bar) : "memory");
}
__device__ __forceinline__ void bulk_st(void* dst, uint32_t src, int bytes) {
  asm volatile("cp.async.bulk.global.shared::cta.bulk_group [%0], [%1], %2;" ::"l"(dst), "r"(src), "r"(bytes) : "memory");
}
__device__ __forceinline__ void tma_st2d(const CUtensorMap* m, uint32_t src, int c0, int c1) {
  asm volatile("cp.async.bulk.tensor.2d.global.shared::cta.bulk_group [%0, {%2, %3}], [%1];" ::"l"(m), "r"(src), "r"(c0), "r"(c1) : "memory");
}
__device__ __forceinline__ void tma_st3d(const CUtensorMap* m, uint32_t src, int c0, int c1, int c2) {
  asm volatile("cp.async.bulk.tensor.3d.global.shared::cta.bulk_group [%0, {%2, %3, %4}], [%1];" ::"l"(m), "r"(src), "r"(c0), "r"(c1), "r"(c2) : "memory");
}
__device__ __forceinline__ void bulk_commit_wait_read() {
  asm volatile("cp.async.bulk.commit_group;" ::: "memory");
  asm volatile("cp.async.bulk.wait_group.read 0;" ::: "memory");
}
__device__ __forceinline__ void bulk_commit_wait() {
  asm volatile("cp.async.bulk.commit_group;" ::: "memory");
  asm volatile("cp.async.bulk.wait_group 0;" ::: "memory");
}
__device__ __forceinline__ void prefetch_l2(const void* p, int bytes) {
  asm volatile("cp.async.bulk.prefetch.L2.global [%0], %1;" ::"l"(p), "r"(bytes) : "memory");
}
__device__ __forceinline__ void wg_fence() { asm volatile("wgmma.fence.sync.aligned;" ::: "memory"); }
__device__ __forceinline__ void wg_commit() { asm volatile("wgmma.commit_group.sync.aligned;" ::: "memory"); }
template <int N> __device__ __forceinline__ void wg_wait() { asm volatile("wgmma.wait_group.sync.aligned %0;" ::"n"(N) : "memory"); }
template <int N> __device__ __forceinline__ void reg_fence(float (&d)[N]) {
#pragma unroll
  for (int i = 0; i < N; i++) asm volatile("" : "+f"(d[i])::"memory");
}
__device__ __forceinline__ void fence_async_smem() { asm volatile("fence.proxy.async.shared::cta;" ::: "memory"); }
__device__ __forceinline__ void fence_async_glb() { asm volatile("fence.proxy.async.global;" ::: "memory"); }
__device__ __forceinline__ uint32_t ld_rlx(const void* p) { uint32_t v; asm volatile("ld.relaxed.gpu.global.b32 %0, [%1];" : "=r"(v) : "l"(p) : "memory"); return v; }
__device__ __forceinline__ uint2 ld_rlx2(const void* p) { uint2 v; asm volatile("ld.relaxed.gpu.global.v2.b32 {%0,%1}, [%2];" : "=r"(v.x), "=r"(v.y) : "l"(p) : "memory"); return v; }
__device__ __forceinline__ uint4 ld_rlx4(const void* p) { uint4 v; asm volatile("ld.relaxed.gpu.global.v4.b32 {%0,%1,%2,%3}, [%4];" : "=r"(v.x), "=r"(v.y), "=r"(v.z), "=r"(v.w) : "l"(p) : "memory"); return v; }
__device__ __forceinline__ uint32_t ld_nc(const void* p) { uint32_t v; asm volatile("ld.global.nc.L1::no_allocate.b32 %0, [%1];" : "=r"(v) : "l"(p) : "memory"); return v; }
__device__ __forceinline__ uint4 ld_nc4(const void* p) { uint4 v; asm volatile("ld.global.nc.v4.b32 {%0,%1,%2,%3}, [%4];" : "=r"(v.x), "=r"(v.y), "=r"(v.z), "=r"(v.w) : "l"(p) : "memory"); return v; }
__device__ __forceinline__ uint32_t lds(uint32_t a) { uint32_t v; asm volatile("ld.shared.b32 %0, [%1];" : "=r"(v) : "r"(a) : "memory"); return v; }
__device__ __forceinline__ uint2 lds2(uint32_t a) { uint2 v; asm volatile("ld.shared.v2.b32 {%0,%1}, [%2];" : "=r"(v.x), "=r"(v.y) : "r"(a) : "memory"); return v; }
__device__ __forceinline__ uint4 lds4(uint32_t a) { uint4 v; asm volatile("ld.shared.v4.b32 {%0,%1,%2,%3}, [%4];" : "=r"(v.x), "=r"(v.y), "=r"(v.z), "=r"(v.w) : "r"(a) : "memory"); return v; }
__device__ __forceinline__ float lds_bf(uint32_t a) { uint32_t v; asm volatile("ld.shared.u16 %0, [%1];" : "=r"(v) : "r"(a) : "memory"); return __uint_as_float(v << 16); }
__device__ __forceinline__ void sts(uint32_t a, uint32_t v) { asm volatile("st.shared.b32 [%0], %1;" ::"r"(a), "r"(v) : "memory"); }
__device__ __forceinline__ void sts2(uint32_t a, uint32_t v0, uint32_t v1) { asm volatile("st.shared.v2.b32 [%0], {%1,%2};" ::"r"(a), "r"(v0), "r"(v1) : "memory"); }
__device__ __forceinline__ void sts4(uint32_t a, uint32_t v0, uint32_t v1, uint32_t v2, uint32_t v3) { asm volatile("st.shared.v4.b32 [%0], {%1,%2,%3,%4};" ::"r"(a), "r"(v0), "r"(v1), "r"(v2), "r"(v3) : "memory"); }
__device__ __forceinline__ void bar_sync(int id, int n) { asm volatile("bar.sync %0, %1;" ::"r"(id), "r"(n) : "memory"); }
__device__ __forceinline__ void bar_arrive(int id, int n) { asm volatile("bar.arrive %0, %1;" ::"r"(id), "r"(n) : "memory"); }
__device__ __forceinline__ void red_add(unsigned* p, unsigned v) { asm volatile("red.relaxed.gpu.global.add.u32 [%0], %1;" ::"l"(p), "r"(v) : "memory"); }
__device__ __forceinline__ bool any(bool p) { return __any_sync(0xffffffffu, p); }
__device__ __forceinline__ void pause(unsigned clks) {
  asm volatile("{\n.reg .pred p;\n.reg .u32 a, b;\nmov.u32 a, %%clock;\nW:\nmov.u32 b, %%clock;\nsub.u32 b, b, a;\nsetp.lt.s32 p, b, %0;\n@p bra.uni W;\n}" ::"r"(clks) : "memory");
}
__device__ __forceinline__ void red_bf16x8(uint32_t* p, const uint4& v) {
  asm volatile("red.relaxed.gpu.global.add.noftz.v4.bf16x2 [%0], {%1,%2,%3,%4};" ::"l"(p), "r"(v.x), "r"(v.y), "r"(v.z), "r"(v.w) : "memory");
}
constexpr int SPIN_MAX = 1 << 20;
__device__ __forceinline__ uint32_t ld_acq(const void* p) { uint32_t v; asm volatile("ld.acquire.gpu.global.b32 %0, [%1];" : "=r"(v) : "l"(p) : "memory"); return v; }
template <bool ACQ = false> __device__ __forceinline__ void wait_cnt(const unsigned* p, unsigned target) {
  int it = 0;
  while (any((int)((ACQ ? ld_acq(p) : ld_rlx(p)) - target) < 0) && ++it < SPIN_MAX) {}
}
__device__ __forceinline__ uint32_t pack_bf16(float lo, float hi) { uint32_t r; asm("cvt.rn.bf16x2.f32 %0, %1, %2;" : "=r"(r) : "f"(hi), "f"(lo)); return r; }
__device__ __forceinline__ float bf_lo(uint32_t v) { return __uint_as_float(v << 16); }
__device__ __forceinline__ float bf_hi(uint32_t v) { return __uint_as_float(v & 0xffff0000u); }
__device__ __forceinline__ uint32_t hadd2(uint32_t a, uint32_t b) { uint32_t r; asm("add.rn.bf16x2 %0, %1, %2;" : "=r"(r) : "r"(a), "r"(b)); return r; }
__device__ __forceinline__ uint32_t hmul2(uint32_t a, uint32_t b) { uint32_t r; asm("mul.rn.bf16x2 %0, %1, %2;" : "=r"(r) : "r"(a), "r"(b)); return r; }
__device__ __forceinline__ uint32_t hfma2(uint32_t a, uint32_t b, uint32_t c) { uint32_t r; asm("fma.rn.bf16x2 %0, %1, %2, %3;" : "=r"(r) : "r"(a), "r"(b), "r"(c)); return r; }
__device__ __forceinline__ float rbf(float x) { uint32_t r; asm("cvt.rn.bf16x2.f32 %0, %1, %2;" : "=r"(r) : "f"(x), "f"(0.0f)); return __uint_as_float(r); }
__device__ __forceinline__ void stmatrix4(uint32_t a, uint32_t r0, uint32_t r1, uint32_t r2, uint32_t r3) {
  asm volatile("stmatrix.sync.aligned.m8n8.x4.shared.b16 [%0], {%1,%2,%3,%4};" ::"r"(a), "r"(r0), "r"(r1), "r"(r2), "r"(r3) : "memory");
}
__device__ __forceinline__ void stmatrix2(uint32_t a, uint32_t r0, uint32_t r1) {
  asm volatile("stmatrix.sync.aligned.m8n8.x2.shared.b16 [%0], {%1,%2};" ::"r"(a), "r"(r0), "r"(r1) : "memory");
}
__device__ __forceinline__ void stmatrix4t(uint32_t a, uint32_t r0, uint32_t r1, uint32_t r2, uint32_t r3) {
  asm volatile("stmatrix.sync.aligned.m8n8.x4.trans.shared.b16 [%0], {%1,%2,%3,%4};" ::"r"(a), "r"(r0), "r"(r1), "r"(r2), "r"(r3) : "memory");
}
__device__ __forceinline__ uint32_t movm(uint32_t a) { uint32_t r; asm("movmatrix.sync.aligned.m8n8.trans.b16 %0, %1;" : "=r"(r) : "r"(a)); return r; }
template <bool ACC> __device__ __forceinline__ void mma16(float* d, uint32_t a0, uint32_t a1, uint32_t a2, uint32_t a3, uint32_t b0, uint32_t b1) {
  if (ACC) asm("mma.sync.aligned.m16n8k16.row.col.f32.bf16.bf16.f32 {%0,%1,%2,%3}, {%4,%5,%6,%7}, {%8,%9}, {%0,%1,%2,%3};"
               : "+f"(d[0]), "+f"(d[1]), "+f"(d[2]), "+f"(d[3]) : "r"(a0), "r"(a1), "r"(a2), "r"(a3), "r"(b0), "r"(b1));
  else asm("mma.sync.aligned.m16n8k16.row.col.f32.bf16.bf16.f32 {%0,%1,%2,%3}, {%4,%5,%6,%7}, {%8,%9}, {%10,%10,%10,%10};"
           : "=f"(d[0]), "=f"(d[1]), "=f"(d[2]), "=f"(d[3]) : "r"(a0), "r"(a1), "r"(a2), "r"(a3), "r"(b0), "r"(b1), "f"(0.f));
}
__device__ __forceinline__ uint32_t pin(uint32_t v) { uint32_t r; asm volatile("shfl.sync.bfly.b32 %0, %1, 0, 31, 0xffffffff;" : "=r"(r) : "r"(v)); return r; }
template <class T> __device__ __forceinline__ T* pin(T* p) {
  const uint64_t a = reinterpret_cast<uint64_t>(p);
  return reinterpret_cast<T*>((uint64_t)pin((uint32_t)a) | ((uint64_t)pin((uint32_t)(a >> 32)) << 32));
}
__device__ __forceinline__ uint32_t upin(uint32_t v) { return __shfl_sync(0xffffffffu, v, 0); }
template <class T> __device__ __forceinline__ T* upin(T* p) {
  const uint64_t a = reinterpret_cast<uint64_t>(p);
  return reinterpret_cast<T*>((uint64_t)upin((uint32_t)a) | ((uint64_t)upin((uint32_t)(a >> 32)) << 32));
}
__device__ __forceinline__ bool elect() {
  uint32_t p;
  asm volatile("{\n.reg .pred P;\nelect.sync _|P, 0xffffffff;\nselp.u32 %0, 1, 0, P;\n}" : "=r"(p));
  return p;
}
__device__ __forceinline__ uint32_t set_tag(uint32_t w, uint32_t tag) { uint32_t r; asm("lop3.b32 %0, %1, 0xfffffffe, %2, 0xea;" : "=r"(r) : "r"(w), "r"(tag)); return r; }
__device__ __forceinline__ uint32_t and_or(uint32_t w, uint32_t a, uint32_t o) { uint32_t r; asm("lop3.b32 %0, %1, %2, %3, 0xea;" : "=r"(r) : "r"(w), "r"(a), "r"(o)); return r; }
__device__ __forceinline__ uint32_t or3(uint32_t a, uint32_t b, uint32_t c) { uint32_t r; asm("lop3.b32 %0, %1, %2, %3, 0xfe;" : "=r"(r) : "r"(a), "r"(b), "r"(c)); return r; }
__device__ __forceinline__ uint32_t diff2(uint32_t a, uint32_t b, uint32_t tag) { uint32_t r; asm("lop3.b32 %0, %1, %2, %3, 0x7e;" : "=r"(r) : "r"(a), "r"(b), "r"(tag)); return r; }
__device__ __forceinline__ float2 cmul(float2 a, float2 b) { return make_float2(a.x * b.x - a.y * b.y, a.x * b.y + a.y * b.x); }

template<int TB> __device__ __forceinline__ void wgmma_ss_160_0(float (&d)[96], uint32_t al, uint32_t ah, uint32_t bl, uint32_t bh) {
  asm volatile("{\n.reg .b64 da, db;\nmov.b64 da, {%80, %81};\nmov.b64 db, {%82, %83};\n"
    "wgmma.mma_async.sync.aligned.m64n160k16.f32.bf16.bf16 {%0,%1,%2,%3,%4,%5,%6,%7,%8,%9,%10,%11,%12,%13,%14,%15,%16,%17,%18,%19,%20,%21,%22,%23,%24,%25,%26,%27,%28,%29,%30,%31,%32,%33,%34,%35,%36,%37,%38,%39,%40,%41,%42,%43,%44,%45,%46,%47,%48,%49,%50,%51,%52,%53,%54,%55,%56,%57,%58,%59,%60,%61,%62,%63,%64,%65,%66,%67,%68,%69,%70,%71,%72,%73,%74,%75,%76,%77,%78,%79}, da, db, 1, 1, 1, 1, %84;\n}\n"
    : "+f"(d[0]),"+f"(d[1]),"+f"(d[2]),"+f"(d[3]),"+f"(d[4]),"+f"(d[5]),"+f"(d[6]),"+f"(d[7]),"+f"(d[8]),"+f"(d[9]),"+f"(d[10]),"+f"(d[11]),"+f"(d[12]),"+f"(d[13]),"+f"(d[14]),"+f"(d[15]),"+f"(d[16]),"+f"(d[17]),"+f"(d[18]),"+f"(d[19]),"+f"(d[20]),"+f"(d[21]),"+f"(d[22]),"+f"(d[23]),"+f"(d[24]),"+f"(d[25]),"+f"(d[26]),"+f"(d[27]),"+f"(d[28]),"+f"(d[29]),"+f"(d[30]),"+f"(d[31]),"+f"(d[32]),"+f"(d[33]),"+f"(d[34]),"+f"(d[35]),"+f"(d[36]),"+f"(d[37]),"+f"(d[38]),"+f"(d[39]),"+f"(d[40]),"+f"(d[41]),"+f"(d[42]),"+f"(d[43]),"+f"(d[44]),"+f"(d[45]),"+f"(d[46]),"+f"(d[47]),"+f"(d[48]),"+f"(d[49]),"+f"(d[50]),"+f"(d[51]),"+f"(d[52]),"+f"(d[53]),"+f"(d[54]),"+f"(d[55]),"+f"(d[56]),"+f"(d[57]),"+f"(d[58]),"+f"(d[59]),"+f"(d[60]),"+f"(d[61]),"+f"(d[62]),"+f"(d[63]),"+f"(d[64]),"+f"(d[65]),"+f"(d[66]),"+f"(d[67]),"+f"(d[68]),"+f"(d[69]),"+f"(d[70]),"+f"(d[71]),"+f"(d[72]),"+f"(d[73]),"+f"(d[74]),"+f"(d[75]),"+f"(d[76]),"+f"(d[77]),"+f"(d[78]),"+f"(d[79])
    : "r"(al), "r"(ah), "r"(bl), "r"(bh), "n"(TB));
}
template<int TB> __device__ __forceinline__ void wgmma_ss_144_0(float (&d)[96], uint32_t al, uint32_t ah, uint32_t bl, uint32_t bh) {
  asm volatile("{\n.reg .b64 da, db;\nmov.b64 da, {%72, %73};\nmov.b64 db, {%74, %75};\n"
    "wgmma.mma_async.sync.aligned.m64n144k16.f32.bf16.bf16 {%0,%1,%2,%3,%4,%5,%6,%7,%8,%9,%10,%11,%12,%13,%14,%15,%16,%17,%18,%19,%20,%21,%22,%23,%24,%25,%26,%27,%28,%29,%30,%31,%32,%33,%34,%35,%36,%37,%38,%39,%40,%41,%42,%43,%44,%45,%46,%47,%48,%49,%50,%51,%52,%53,%54,%55,%56,%57,%58,%59,%60,%61,%62,%63,%64,%65,%66,%67,%68,%69,%70,%71}, da, db, 1, 1, 1, 1, %76;\n}\n"
    : "+f"(d[0]),"+f"(d[1]),"+f"(d[2]),"+f"(d[3]),"+f"(d[4]),"+f"(d[5]),"+f"(d[6]),"+f"(d[7]),"+f"(d[8]),"+f"(d[9]),"+f"(d[10]),"+f"(d[11]),"+f"(d[12]),"+f"(d[13]),"+f"(d[14]),"+f"(d[15]),"+f"(d[16]),"+f"(d[17]),"+f"(d[18]),"+f"(d[19]),"+f"(d[20]),"+f"(d[21]),"+f"(d[22]),"+f"(d[23]),"+f"(d[24]),"+f"(d[25]),"+f"(d[26]),"+f"(d[27]),"+f"(d[28]),"+f"(d[29]),"+f"(d[30]),"+f"(d[31]),"+f"(d[32]),"+f"(d[33]),"+f"(d[34]),"+f"(d[35]),"+f"(d[36]),"+f"(d[37]),"+f"(d[38]),"+f"(d[39]),"+f"(d[40]),"+f"(d[41]),"+f"(d[42]),"+f"(d[43]),"+f"(d[44]),"+f"(d[45]),"+f"(d[46]),"+f"(d[47]),"+f"(d[48]),"+f"(d[49]),"+f"(d[50]),"+f"(d[51]),"+f"(d[52]),"+f"(d[53]),"+f"(d[54]),"+f"(d[55]),"+f"(d[56]),"+f"(d[57]),"+f"(d[58]),"+f"(d[59]),"+f"(d[60]),"+f"(d[61]),"+f"(d[62]),"+f"(d[63]),"+f"(d[64]),"+f"(d[65]),"+f"(d[66]),"+f"(d[67]),"+f"(d[68]),"+f"(d[69]),"+f"(d[70]),"+f"(d[71])
    : "r"(al), "r"(ah), "r"(bl), "r"(bh), "n"(TB));
}
template<int TB> __device__ __forceinline__ void wgmma_ss_96_0(float (&d)[96], uint32_t al, uint32_t ah, uint32_t bl, uint32_t bh) {
  asm volatile("{\n.reg .b64 da, db;\nmov.b64 da, {%48, %49};\nmov.b64 db, {%50, %51};\n"
    "wgmma.mma_async.sync.aligned.m64n96k16.f32.bf16.bf16 {%0,%1,%2,%3,%4,%5,%6,%7,%8,%9,%10,%11,%12,%13,%14,%15,%16,%17,%18,%19,%20,%21,%22,%23,%24,%25,%26,%27,%28,%29,%30,%31,%32,%33,%34,%35,%36,%37,%38,%39,%40,%41,%42,%43,%44,%45,%46,%47}, da, db, 1, 1, 1, 1, %52;\n}\n"
    : "+f"(d[0]),"+f"(d[1]),"+f"(d[2]),"+f"(d[3]),"+f"(d[4]),"+f"(d[5]),"+f"(d[6]),"+f"(d[7]),"+f"(d[8]),"+f"(d[9]),"+f"(d[10]),"+f"(d[11]),"+f"(d[12]),"+f"(d[13]),"+f"(d[14]),"+f"(d[15]),"+f"(d[16]),"+f"(d[17]),"+f"(d[18]),"+f"(d[19]),"+f"(d[20]),"+f"(d[21]),"+f"(d[22]),"+f"(d[23]),"+f"(d[24]),"+f"(d[25]),"+f"(d[26]),"+f"(d[27]),"+f"(d[28]),"+f"(d[29]),"+f"(d[30]),"+f"(d[31]),"+f"(d[32]),"+f"(d[33]),"+f"(d[34]),"+f"(d[35]),"+f"(d[36]),"+f"(d[37]),"+f"(d[38]),"+f"(d[39]),"+f"(d[40]),"+f"(d[41]),"+f"(d[42]),"+f"(d[43]),"+f"(d[44]),"+f"(d[45]),"+f"(d[46]),"+f"(d[47])
    : "r"(al), "r"(ah), "r"(bl), "r"(bh), "n"(TB));
}
template<int TB> __device__ __forceinline__ void wgmma_ss_96_48(float (&d)[96], uint32_t al, uint32_t ah, uint32_t bl, uint32_t bh) {
  asm volatile("{\n.reg .b64 da, db;\nmov.b64 da, {%48, %49};\nmov.b64 db, {%50, %51};\n"
    "wgmma.mma_async.sync.aligned.m64n96k16.f32.bf16.bf16 {%0,%1,%2,%3,%4,%5,%6,%7,%8,%9,%10,%11,%12,%13,%14,%15,%16,%17,%18,%19,%20,%21,%22,%23,%24,%25,%26,%27,%28,%29,%30,%31,%32,%33,%34,%35,%36,%37,%38,%39,%40,%41,%42,%43,%44,%45,%46,%47}, da, db, 1, 1, 1, 1, %52;\n}\n"
    : "+f"(d[48]),"+f"(d[49]),"+f"(d[50]),"+f"(d[51]),"+f"(d[52]),"+f"(d[53]),"+f"(d[54]),"+f"(d[55]),"+f"(d[56]),"+f"(d[57]),"+f"(d[58]),"+f"(d[59]),"+f"(d[60]),"+f"(d[61]),"+f"(d[62]),"+f"(d[63]),"+f"(d[64]),"+f"(d[65]),"+f"(d[66]),"+f"(d[67]),"+f"(d[68]),"+f"(d[69]),"+f"(d[70]),"+f"(d[71]),"+f"(d[72]),"+f"(d[73]),"+f"(d[74]),"+f"(d[75]),"+f"(d[76]),"+f"(d[77]),"+f"(d[78]),"+f"(d[79]),"+f"(d[80]),"+f"(d[81]),"+f"(d[82]),"+f"(d[83]),"+f"(d[84]),"+f"(d[85]),"+f"(d[86]),"+f"(d[87]),"+f"(d[88]),"+f"(d[89]),"+f"(d[90]),"+f"(d[91]),"+f"(d[92]),"+f"(d[93]),"+f"(d[94]),"+f"(d[95])
    : "r"(al), "r"(ah), "r"(bl), "r"(bh), "n"(TB));
}
__device__ __forceinline__ void wgmma_rs_72(float (&d)[36], uint32_t a0, uint32_t a1, uint32_t a2, uint32_t a3, uint32_t bl, uint32_t bh, int sd) {
  asm volatile("{\n.reg .pred p;\n.reg .b64 db;\nsetp.ne.b32 p, %42, 0;\nmov.b64 db, {%40, %41};\n"
    "wgmma.mma_async.sync.aligned.m64n72k16.f32.bf16.bf16 {%0,%1,%2,%3,%4,%5,%6,%7,%8,%9,%10,%11,%12,%13,%14,%15,%16,%17,%18,%19,%20,%21,%22,%23,%24,%25,%26,%27,%28,%29,%30,%31,%32,%33,%34,%35}, {%36,%37,%38,%39}, db, p, 1, 1, 1;\n}\n"
    : "+f"(d[0]),"+f"(d[1]),"+f"(d[2]),"+f"(d[3]),"+f"(d[4]),"+f"(d[5]),"+f"(d[6]),"+f"(d[7]),"+f"(d[8]),"+f"(d[9]),"+f"(d[10]),"+f"(d[11]),"+f"(d[12]),"+f"(d[13]),"+f"(d[14]),"+f"(d[15]),"+f"(d[16]),"+f"(d[17]),"+f"(d[18]),"+f"(d[19]),"+f"(d[20]),"+f"(d[21]),"+f"(d[22]),"+f"(d[23]),"+f"(d[24]),"+f"(d[25]),"+f"(d[26]),"+f"(d[27]),"+f"(d[28]),"+f"(d[29]),"+f"(d[30]),"+f"(d[31]),"+f"(d[32]),"+f"(d[33]),"+f"(d[34]),"+f"(d[35])
    : "r"(a0), "r"(a1), "r"(a2), "r"(a3), "r"(bl), "r"(bh), "r"(sd));
}
__device__ __forceinline__ void wgmma_rs_48(float (&d)[24], uint32_t a0, uint32_t a1, uint32_t a2, uint32_t a3, uint32_t bl, uint32_t bh, int sd) {
  asm volatile("{\n.reg .pred p;\n.reg .b64 db;\nsetp.ne.b32 p, %30, 0;\nmov.b64 db, {%28, %29};\n"
    "wgmma.mma_async.sync.aligned.m64n48k16.f32.bf16.bf16 {%0,%1,%2,%3,%4,%5,%6,%7,%8,%9,%10,%11,%12,%13,%14,%15,%16,%17,%18,%19,%20,%21,%22,%23}, {%24,%25,%26,%27}, db, p, 1, 1, 1;\n}\n"
    : "+f"(d[0]),"+f"(d[1]),"+f"(d[2]),"+f"(d[3]),"+f"(d[4]),"+f"(d[5]),"+f"(d[6]),"+f"(d[7]),"+f"(d[8]),"+f"(d[9]),"+f"(d[10]),"+f"(d[11]),"+f"(d[12]),"+f"(d[13]),"+f"(d[14]),"+f"(d[15]),"+f"(d[16]),"+f"(d[17]),"+f"(d[18]),"+f"(d[19]),"+f"(d[20]),"+f"(d[21]),"+f"(d[22]),"+f"(d[23])
    : "r"(a0), "r"(a1), "r"(a2), "r"(a3), "r"(bl), "r"(bh), "r"(sd));
}
template<int N,int OFF,int TB> __device__ __forceinline__ void wgmma_ss(float (&d)[96], uint32_t al, uint32_t ah, uint32_t bl, uint32_t bh) {
  if constexpr (N==160 && OFF==0) wgmma_ss_160_0<TB>(d, al, ah, bl, bh);
  else if constexpr (N==144 && OFF==0) wgmma_ss_144_0<TB>(d, al, ah, bl, bh);
  else if constexpr (N==96 && OFF==0) wgmma_ss_96_0<TB>(d, al, ah, bl, bh);
  else if constexpr (N==96 && OFF==48) wgmma_ss_96_48<TB>(d, al, ah, bl, bh);
}

__device__ __forceinline__ void dft3(float2& a, float2& b, float2& c) {
  const float s = 0.86602540378443864676f;
  float2 t = make_float2(b.x + c.x, b.y + c.y), d = make_float2(b.x - c.x, b.y - c.y);
  float2 m = make_float2(fmaf(-0.5f, t.x, a.x), fmaf(-0.5f, t.y, a.y));
  a = make_float2(a.x + t.x, a.y + t.y);
  b = make_float2(fmaf(s, d.y, m.x), fmaf(-s, d.x, m.y));
  c = make_float2(fmaf(-s, d.y, m.x), fmaf(s, d.x, m.y));
}
__device__ __forceinline__ void dft9(float2 (&x)[9]) {
  const float2 w1 = make_float2(0.76604444311897803520f, -0.64278760968653932632f);
  const float2 w2 = make_float2(0.17364817766693034885f, -0.98480775301220805937f);
  const float2 w4 = make_float2(-0.93969262078590838405f, -0.34202014332566873304f);
  dft3(x[0], x[3], x[6]); dft3(x[1], x[4], x[7]); dft3(x[2], x[5], x[8]);
  x[4] = cmul(x[4], w1); x[7] = cmul(x[7], w2); x[5] = cmul(x[5], w2); x[8] = cmul(x[8], w4);
  dft3(x[0], x[1], x[2]); dft3(x[3], x[4], x[5]); dft3(x[6], x[7], x[8]);
  float2 t;
  t = x[1]; x[1] = x[3]; x[3] = t;
  t = x[2]; x[2] = x[6]; x[6] = t;
  t = x[5]; x[5] = x[7]; x[7] = t;
}

__device__ __forceinline__ uint32_t* mod_ptr(Scratch* sc, int u, int t128) {
  const int i = t128 & 15;
  return u < 72 ? sc->moda + (t128 >> 4) * (2 * D_) + 16 * u + 2 * (i & 7) + (i >> 3) : sc->mod + 16 * (u - 72) + i;
}
__device__ __forceinline__ void mod_unit(Scratch* sc, int u, int t128, uint32_t sw_, uint32_t bar, int ph, uint32_t rb, uint32_t tag) {
  const int w = t128 >> 5, l = t128 & 31;
  uint32_t b[18];
#pragma unroll
  for (int i = 0; i < 18; i++) b[i] = lds(red + 512 + (72 * w + 4 * i + (l & 3)) * 4);
  const uint32_t sa = pin(sw_ + (144 * w + (l & 7) + 8 * (l >> 4)) * 32 + (((l >> 3) ^ (l >> 2)) & 1) * 16);
  const uint32_t sr = pin(rb + (l >> 2) * 16 + w * 4);
  uint32_t* const dst = pin(mod_ptr(sc, u, t128));
  const int kind = u / 36;
  const float mul = __uint_as_float(pin(__float_as_uint(kind == 0 ? 16.0f : 1.0f))), add = __uint_as_float(pin(__float_as_uint(kind == 1 || kind == 4 ? 1.0f : 0.0f)));
  mbar_wait(bar, ph);
  if (t128 == 0 && u < 72) TS(10);
  float d[3][4];
#pragma unroll
  for (int i = 0; i < 9; i++) {
    uint32_t a0, a1, a2, a3;
    asm volatile("ldmatrix.sync.aligned.m8n8.x4.trans.shared.b16 {%0,%1,%2,%3}, [%4];" : "=r"(a0), "=r"(a1), "=r"(a2), "=r"(a3) : "r"(sa + i * 512) : "memory");
    if (i < 3) mma16<false>(d[i], a0, a1, a2, a3, b[2 * i], b[2 * i + 1]);
    else mma16<true>(d[i % 3], a0, a1, a2, a3, b[2 * i], b[2 * i + 1]);
  }
  if ((l & 3) == 0) { sts(sr, __float_as_uint(d[0][0] + d[1][0] + d[2][0])); sts(sr + 128, __float_as_uint(d[0][2] + d[1][2] + d[2][2])); }
  bar_sync(4, 128);
  const uint4 v = lds4(rb + (l & 15) * 16);
  const float m = rbf(fmaf(rbf((__uint_as_float(v.x) + __uint_as_float(v.y)) + (__uint_as_float(v.z) + __uint_as_float(v.w))), mul, add));
  if (u < 72 || t128 < 16) *dst = __float_as_uint(m) | tag;
}

__device__ __forceinline__ float rsq(float x) { float r; asm("rsqrt.approx.ftz.f32 %0, %1;" : "=f"(r) : "f"(x)); return r; }
__device__ __forceinline__ void ln_stats2(const float (&a)[18], const float (&b)[18], float sc, float& oa, float& ra, float& ob, float& rb) {
  float v[4] = {0.f, 0.f, 0.f, 0.f}, w[4] = {0.f, 0.f, 0.f, 0.f};
#pragma unroll
  for (int i = 0; i < 18; i += 2) {
    v[0] += a[i]; v[1] = fmaf(a[i], a[i], v[1]); v[2] += b[i]; v[3] = fmaf(b[i], b[i], v[3]);
    w[0] += a[i + 1]; w[1] = fmaf(a[i + 1], a[i + 1], w[1]); w[2] += b[i + 1]; w[3] = fmaf(b[i + 1], b[i + 1], w[3]);
  }
#pragma unroll
  for (int e = 0; e < 4; e++) v[e] += w[e];
#pragma unroll
  for (int o = 16; o; o >>= 1) {
#pragma unroll
    for (int e = 0; e < 4; e++) v[e] += __shfl_xor_sync(0xffffffffu, v[e], o);
  }
  const float ma = v[0] * (1.0f / D_), mb = v[2] * (1.0f / D_);
  ra = sc * rsq(fmaxf(fmaf(-ma, ma, v[1] * (1.0f / D_)), 0.f) + 1e-5f);
  rb = sc * rsq(fmaxf(fmaf(-mb, mb, v[3] * (1.0f / D_)), 0.f) + 1e-5f);
  oa = -ma * ra; ob = -mb * rb;
}

__device__ __forceinline__ float tmat(int c, int q, int j) {
  const int ph = q == 1 ? 1024 * j : (q >> 1) * (c + 128 * j) + 512 * (q & 1);
  return __cosf((float)(((ph + 1024) & 2047) - 1024) * (6.283185307179586f / 2048.0f));
}
__device__ __forceinline__ uint32_t line_off(int k1, int kap, int pi, int f) {
  int kd = 64 * k1 + 9 * kap;
  if (kap == 0 && k1 > 4) kd -= 288;
  if (kd >= D_) kd -= D_;
  return pi * 2400 + ((min(kd, D_ - kd) ^ f) << 3);
}

constexpr int JSK = 5;
struct Ring { uint32_t st, ph; };
template <bool G2, class T> __device__ __forceinline__ void ring_next(T& st, T& ph) {
  if (++st == NST) st = 0;
  ph ^= ((G2 ? 0xDu : 0x1u) >> st) & 1;
}
__device__ __forceinline__ void arrive_if(uint32_t a, uint32_t p) {
  asm volatile("{\n.reg .pred p;\nsetp.ne.u32 p, %1, 0;\n@p mbarrier.arrive.shared::cta.b64 _, [%0];\n}" ::"r"(a), "r"(p) : "memory");
}
template <int NA> __device__ __forceinline__ void reg_fence_n(float (&d)[96]) {
#pragma unroll
  for (int i = 0; i < NA; i++) asm volatile("" : "+f"(d[i])::"memory");
}
template <int MODE>
__device__ __forceinline__ void gemm_main(float (&acc)[96], uint32_t da0, uint32_t da1, uint32_t db0, int wg, Ring& rg,
                                          uint32_t* x1p, const uint32_t (&xr)[18]) {
  static_assert(JSK == NST - 1, "the held slot is the first one that is not refilled by GEMM1");
  constexpr int NKB = MODE == 3 ? 36 : 32;
  constexpr uint32_t HA = 0x40000040u, HB = MODE == 3 ? 0x40000040u : 0x80000020u;
  constexpr uint32_t KA = 2048 >> 4, KB = MODE == 3 ? (32 >> 4) : (1024 >> 4);
  constexpr int NA = MODE == 3 ? 72 : MODE == 1 ? 96 : 80;
  const uint32_t t = threadIdx.x & 127;
  const uint32_t eb = full0 + 8 * NST;
  uint32_t pb = 0, rel = t == 0, prel = 0, ok = 0;
  int n = MODE == 3 ? NKB - JSK : X1K + 2 * wg;
#pragma unroll 1
  for (int pass = MODE == 3 ? 0 : -1;; pass++) {
#pragma unroll 1
    do {
      const uint32_t so = rg.st * ((MODE == 3 ? STAGE2 : STAGE) >> 4), cb = eb + 8 * rg.st;
      if (__builtin_expect(!ok, 0)) mbar_wait(full0 + 8 * rg.st, rg.ph);
      reg_fence_n<NA>(acc);
      if (MODE == 1 && wg) {
        wg_fence();
#pragma unroll
        for (int k = 0; k < 4; k++) wgmma_ss<96, 48, 1>(acc, da1 + so + k * KA, HA, db0 + so + k * KB, HB);
        wg_commit();
      }
      wg_fence();
#pragma unroll
      for (int k = 0; k < 4; k++) {
        if (k == 3) { ring_next<MODE == 3>(rg.st, rg.ph); ok = PEEK ? mbar_test(full0 + 8 * rg.st, rg.ph) : 0; }
        if (MODE == 0) wgmma_ss<160, 0, 1>(acc, da0 + so + k * KA, HA, db0 + so + k * KB, HB);
        else if (MODE == 3) wgmma_ss<144, 0, 0>(acc, da0 + so + k * KA, HA, db0 + so + k * KB, HB);
        else wgmma_ss<96, 0, 1>(acc, da0 + so + k * KA, HA, db0 + so + k * KB, HB);
      }
      wg_commit();
      wg_wait<1>();
      reg_fence_n<NA>(acc);
      arrive_if(pb, prel);
      pb = cb; prel = rel;
    } while (--n);
    if (pass == 2 - wg) break;
    if (MODE != 3 && pass < 0) {
      if (blockIdx.x < 128) {
#pragma unroll
        for (int i = 0; i < 9; i++) { x1p[32 * i] = xr[i]; x1p[128 * 288 + 32 * i] = xr[9 + i]; }
      }
      n = NKB - JSK - X1K - 2 * wg;
      continue;
    }
    n = 1;
    if (pass == 0) {
      if (MODE != 3) prel = rel & wg;
      else prel = rel = 0;
      n = JSK - 1 + wg;
      if (!wg) continue;
      wg_wait<0>();
      arrive_if(pb, prel);
      prel = 0;
    }
    bar_sync(1, 256);
  }
  wg_wait<0>();
  reg_fence_n<NA>(acc);
  if (MODE != 3) arrive_if(pb, MODE == 1 ? prel & ~wg : prel);
}

constexpr float GK1 = 2.0f * 0.7978845608028654f, GK3 = 8.0f * 0.044715f * 0.7978845608028654f;

__device__ __forceinline__ int kb2_order(int i) { const int wv = i / 6; return 6 * (i - 6 * wv) + ((0x431250 >> (4 * wv)) & 7); }

__device__ __forceinline__ void wait_flags(const unsigned* base, int n, int idx, unsigned target, uint64_t& ready) {
  if ((ready >> idx) & 1) return;
  const int l = threadIdx.x & 31;
  int it = 0;
  while (true) {
    unsigned a = ld_rlx(base + l), b = l + 32 < n ? ld_rlx(base + l + 32) : target;
    ready = (uint64_t)__ballot_sync(0xffffffffu, (int)(a - target) >= 0) | ((uint64_t)__ballot_sync(0xffffffffu, (int)(b - target) >= 0) << 32);
    if (((ready >> idx) & 1) || ++it > SPIN_MAX) break;
  }
}

enum { B_FULL = 0, B_EMPTY = 6, B_S4 = 12, B_S5, B_LAND, B_FLT = B_LAND + 6, B_Z1, B_Z2, B_GO, B_X, B_WM, B_NUM, B_W0 = B_NUM };

__global__ void __launch_bounds__(NTHR, 1)
fused_kernel(const Params p, const __grid_constant__ Maps maps) {
  extern __shared__ __align__(1024) uint8_t smem_raw[];
  const int tid = threadIdx.x, cta = blockIdx.x, t128 = tid & 127;
  const int wp = __shfl_sync(0xffffffffu, tid >> 5, 0), wg = wp >> 2;
  const int l = tid & 31, g = l >> 2, t = l & 3;
  Scratch* const sc = p.s;
  const bool rows = cta < 128;
  const int R = cta - 12;

  uint32_t xr[18];
  uint32_t cv[3];
  const unsigned ep = ld_rlx(&sc->cnt[C_EP]) + 1;
  if (tid == 0) TS(0);
  if (wg == 2) {
#pragma unroll
    for (int i = 0; i < 3; i++) cv[i] = ld_nc(reinterpret_cast<const uint32_t*>(p.c) + min(t128 + 128 * i, 287));
    if (wp == 9 && l < 9 && rows) {
      const int h = 9 * cta + l;
      prefetch_l2(reinterpret_cast<const uint8_t*>(p.wmod) + (size_t)(h >> 1) * (12 * D_) + (h & 1) * (2 * D_), 2 * D_);
    }
    if (tid == 256 && cta < 72) {
      mbar_init(full0 + 8 * B_W0, 1);
      fence_async_smem();
      mbar_expect(full0 + 8 * B_W0, 18432);
#pragma unroll 1
      for (int i = 0; i < 3; i++) tma2d(sbase + O_P2 + i * 6144, &maps.wm, 16 * cta, 192 * i, full0 + 8 * B_W0);
    }
    __syncwarp();
#pragma unroll 1
    for (int u = cta < 72 ? cta : 72 + cta; u < 216; u += u < 72 ? 72 : NCTA) if (u < 72 || t128 < 16) *mod_ptr(sc, u, t128) = 0;
    if (wp == 11 && smem_u32(smem_raw) != sbase) __trap();
    if (wp >= 10 && elect()) {
#pragma unroll 1
      for (int i = wp - 10; i < B_NUM; i += 2) mbar_init(full0 + 8 * i, i == B_FLT ? 4 : i == B_WM ? 3 : i < B_LAND ? 2 : 1);
      fence_async_smem();
    }
    __syncwarp();
  }
  CK(0);
  auto load_x = [&]() {
    const uint32_t* xs = reinterpret_cast<const uint32_t*>(p.x) + (size_t)(cta + 256 * wp) * 288 + l;
#pragma unroll
    for (int i = 0; i < 9; i++) { xr[i] = ld_nc(xs + 32 * i); xr[9 + i] = ld_nc(xs + 128 * 288 + 32 * i); }
  };
  if (rows && wg < 2) load_x();
  if (tid == 64 && cta == NCTA - 1) prefetch_l2(p.tab, sizeof(T_TAB));
  __syncwarp();
  const uint32_t tag16 = (ep & 0x7fffu) | 0x8000u, tag1 = ep & 1u;

  if (wg == 2) {
#pragma unroll
    for (int i = 0; i < 3; i++) {
      const float c0 = bf_lo(cv[i]), c1 = bf_hi(cv[i]);
      sts(red + 512 + min(t128 + 128 * i, 287) * 4, pack_bf16(__fdividef(c0, 1.0f + __expf(-c0)), __fdividef(c1, 1.0f + __expf(-c1))));
    }
    if (wp == 9 && l < 12) asm volatile("prefetch.tensormap [%0];" ::"l"(&maps.z1 + l) : "memory");
    bar_sync(4, 128);
    if (cta < 72) {
      mod_unit(sc, cta, t128, sbase + O_P2, full0 + 8 * B_W0, 0, red, tag16);
      if (t128 == 0) TS(25);
    }
    CK(1);
  }
  const int pi = R / 15, col0 = 20 * (R - 15 * pi);
  const int xu = DF_ * pi + col0, xv = DF_ * (pi ? 16 - pi : 8) + col0;
  auto load_filter = [&](int a) {
    const int x = (a & 1) ? xv : xu;
    const bool wide = (x & 15) > 12;
    mbar_expect(full0 + 8 * B_FLT, wide ? 12288 : 8192);
    tma2d(sbase + O_RAW + a * 12288, &maps.wf[a & 2], x & ~15, 0, full0 + 8 * B_FLT);
    if (wide) tma2d(sbase + O_RAW + a * 12288 + 8192, &maps.wf[(a & 2) + 1], (x & ~15) + 32, 0, full0 + 8 * B_FLT);
  };
  const int kap = 8 * ((wp & 3) ^ (wg & 1)) + g;
  uint4 af[4];
  if (rows) {
    uint32_t tb[4];
#pragma unroll
    for (int i = 0; i < 4; i++) tb[i] = pack_bf16(tmat(cta, 8 * (i >> 1) + g, 2 * t + 8 * (i & 1)), tmat(cta, 8 * (i >> 1) + g, 2 * t + 8 * (i & 1) + 1));
    uint32_t sb1[3], lo[9];
#pragma unroll
    for (int i = 0; i < 4; i++) tb[i] = pin(tb[i]);
#pragma unroll
    for (int i = 0; i < 3; i++) {
      const int d = 48 * wp + 16 * i + (l & 15);
      sb1[i] = pin(sbase + O_B1 + (l >> 4) * 9216 + (d % 9) * 1024 + (d & 63) * 16);
    }
    const uint32_t snt = pin(sbase + O_NRM + ((l & 7) + 8 * (l >> 4)) * 1168 + (48 * wp + (l & 8)) * 2);
    uint2 ms[3], mc[3];
    const uint32_t smask = pin(t ? 0u : 0xffff0000u);
    const uint32_t* const mp = pin(sc->moda + (cta >> 4) * (2 * D_) + 48 * wp + 2 * g);
    auto load_mod = [&]() {
#pragma unroll
      for (int i = 0; i < 3; i++) { ms[i] = ld_rlx2(mp + 16 * i); mc[i] = ld_rlx2(mp + D_ + 16 * i); }
    };
    if (wg < 2) {
#pragma unroll
      for (int k1 = 0; k1 < 9; k1++) lo[k1] = pin(sbase + O_Z1 + line_off(k1, kap, 4 * wg + t, cta & 3));
      float a[18], b[18];
#pragma unroll
      for (int i = 0; i < 9; i++) { a[2 * i] = bf_lo(xr[i]); a[2 * i + 1] = bf_hi(xr[i]); b[2 * i] = bf_lo(xr[9 + i]); b[2 * i + 1] = bf_hi(xr[9 + i]); }
      float oa, ra, ob, rb;
      ln_stats2(a, b, 1.0f, oa, ra, ob, rb);
      CK(1);
      const uint32_t sn = sbase + O_NRM + wp * 2336 + l * 4;
#pragma unroll
      for (int i = 0; i < 9; i++) {
        sts(sn + i * 128, pack_bf16(fmaf(a[2 * i], ra, oa), fmaf(a[2 * i + 1], ra, oa)));
        sts(sn + 1168 + i * 128, pack_bf16(fmaf(b[2 * i], rb, ob), fmaf(b[2 * i + 1], rb, ob)));
      }
      CK(2);
      bar_arrive(10, NTHR);
      load_mod();
#pragma unroll
      for (int kk = 0; kk < 4; kk++) af[kk] = ld_nc4(p.tab + TB_F + kk * 128 + (t128 ^ (wg << 5)));
      bar_sync(1, 256);
      if (tid == 0) TS(2);
    } else {
      bar_sync(10, NTHR);
      load_mod();
      CK(2);
      if (PFF && wp >= 12 - PFF && elect()) prefetch_l2(reinterpret_cast<const uint8_t*>(wp == 10 ? p.wr : p.wi) + cta * 9248, 9248);
      __syncwarp();
    }
    float rs[3][8];
#pragma unroll
    for (int i = 0; i < 3; i++) {
      uint32_t a0, a1, a2, a3;
      asm volatile("ldmatrix.sync.aligned.m8n8.x4.trans.shared.b16 {%0,%1,%2,%3}, [%4];" : "=r"(a0), "=r"(a1), "=r"(a2), "=r"(a3)
                   : "r"(snt + 32 * i) : "memory");
      mma16<false>(&rs[i][0], a0, a1, a2, a3, tb[0], tb[1]);
      mma16<false>(&rs[i][4], a0, a1, a2, a3, tb[2], tb[3]);
    }
    CK(3);
    {
      int it = 0;
#pragma unroll 1
      while (true) {
        uint32_t bad = 0;
#pragma unroll
        for (int i = 0; i < 3; i++) bad |= diff2(ms[i].x, ms[i].y, tag16) | diff2(mc[i].x, mc[i].y, tag16);
        if (!any(bad & 0xffffu) || ++it > SPIN_MAX) break;
        load_mod();
      }
      CK(4);
      if (tid == 0) TS(3);
#pragma unroll
      for (int i = 0; i < 3; i++) {
        const float c0 = bf_hi(mc[i].x), c1 = bf_hi(mc[i].y);
        const float s0 = __uint_as_float(ms[i].x & smask), s1 = __uint_as_float(ms[i].y & smask);
        stmatrix4(sb1[i], pack_bf16(fmaf(rs[i][0], c0, s0), rs[i][1] * c0), pack_bf16(fmaf(rs[i][2], c1, s1), rs[i][3] * c1),
                  pack_bf16(rs[i][4] * c0, rs[i][5] * c0), pack_bf16(rs[i][6] * c1, rs[i][7] * c1));
      }
    }
    fence_async_smem();
    CK(5);
    if (wg == 2) {
      bar_arrive(5, NTHR);
      if (R >= 0 && elect()) load_filter(wp - 8);
      __syncwarp();
    } else {
      bar_sync(5, NTHR);
      CK(6);
      float acc[36];
      const uint32_t db = (((sbase + O_B1 + wg * 9216) & 0x3FFFF) >> 4) | ((128 >> 4) << 16);
      wg_fence();
#pragma unroll
      for (int kk = 0; kk < 4; kk++) wgmma_rs_72(acc, af[kk].x, af[kk].y, af[kk].z, af[kk].w, db + kk * 16, 1024 >> 4, kk);
      wg_commit();
      wg_wait<0>();
      reg_fence(acc);
      CK(7);
      float2 za[9], zb[9];
#pragma unroll
      for (int i = 0; i < 9; i++) { za[i] = make_float2(acc[4 * i], acc[4 * i + 2]); zb[i] = make_float2(acc[4 * i + 1], acc[4 * i + 3]); }
      dft9(za); dft9(zb);
      if (kap == 0) {
#pragma unroll
        for (int k = 1; k < 5; k++) {
          float2 a = za[k], b = za[9 - k];
          za[k] = make_float2(a.x + b.x, a.y - b.y); za[9 - k] = make_float2(a.y + b.y, b.x - a.x);
          a = zb[k]; b = zb[9 - k];
          zb[k] = make_float2(a.x + b.x, a.y - b.y); zb[9 - k] = make_float2(a.y + b.y, b.x - a.x);
        }
        sts2(lo[0] + 288 * 8, set_tag(pack_bf16(za[0].y, 0.f), tag1), pack_bf16(zb[0].y, 0.f));
        za[0].y = 0.f; zb[0].y = 0.f;
      }
      __syncwarp();
#pragma unroll
      for (int k1 = 0; k1 < 9; k1++) sts2(lo[k1], set_tag(pack_bf16(za[k1].x, za[k1].y), tag1), pack_bf16(zb[k1].x, zb[k1].y));
      fence_async_smem();
      CK(8);
      bar_arrive(2 + wg, 160);
      {
        const uint32_t fx = (((cta >> 4) ^ cta) & 3) << 3, dl = O_IN - O_Z1, st = sbase + O_ST + 15360 + tid * 16;
        sts4(st, (lo[0] ^ fx) + dl, (lo[1] ^ fx) + dl, (lo[2] ^ fx) + dl, (lo[3] ^ fx) + dl);
        sts4(st + 4096, (lo[4] ^ fx) + dl, (lo[5] ^ fx) + dl, (lo[6] ^ fx) + dl, (lo[7] ^ fx) + dl);
        sts4(st + 8192, (lo[8] ^ fx) + dl, (lo[0] ^ fx) + dl + (kap ? 0 : 288 * 8),
             sbase + O_B3 + wg * 1024 + (l >> 4) * 2048 + (2 * (kap & 24) + (l & 15)) * 16, 0);
      }
    }
    {
      uint32_t sy[6];
#pragma unroll
      for (int i = 0; i < 6; i++) {
        const int rr = 16 * (wp & 3) + g + 8 * (i & 1);
        sy[i] = sbase + O_Y + (t * 584 + 64 * ((3 * wg + (i >> 1) + 63 - rr) % 9) + rr) * 4;
      }
      sts4(sbase + O_ST + tid * 16, movm(tb[0]), movm(tb[2]), movm(tb[1]), movm(tb[3]));
      sts4(sbase + O_ST + 6144 + tid * 16, sy[0], sy[1], sy[2], sy[3]);
      sts2(sbase + O_ST + 12288 + tid * 8, sy[4], sy[5]);
    }
  } else {
    __syncthreads();
  }

  if ((wp >> 1) == 4) {
    if (rows) {
      const int slot = 4 * (cta & 7) + ((cta >> 4) & 3) + 32 * (2 * (cta >> 6) + ((cta >> 3) & 1));
      const uint32_t c0 = upin(40 * slot), c1 = upin(60 * (wp - 8)), src = upin(sbase + O_Z1 + (wp - 8) * 9600);
      const CUtensorMap* mp = upin(&maps.z1);
      unsigned* hint = pin(&sc->cnt[C_Z1 + 32 * (wp - 8)]);
      bar_sync(wp - 6, 160);
      if (elect()) {
        tma_st2d(mp, src, c0, c1);
        HW();
        red_add(hint, 1);
        if (wp == 8) TS(4);
      }
    } else {
      int it = 0;
      while (any((ld_rlx(sc->moda + 36 * l) ^ tag16) & 0xffffu) && ++it < SPIN_MAX) {}
      if (elect()) { load_filter(wp - 8); load_filter(wp - 6); }
    }
    __syncwarp();
  }
  auto load_wm = [&](int u) {
    if (wp > 8 && elect()) {
      mbar_expect(full0 + 8 * B_WM, 6144);
      tma2d(sbase + O_NRM + (wp - 9) * 6144, &maps.wm, 16 * u, 192 * (wp - 9), full0 + 8 * B_WM);
    }
    __syncwarp();
  };
  if (R >= 0) {
    const int nl = (col0 + wp < DF_) + (wg < 2 && col0 + wp + 12 < DF_);
    uint4 cf[2][4], G[4];
#pragma unroll
    for (int i = 0; i < 4; i++) {
      cf[0][i] = __ldg(p.tab + TB_P2 + i * 32 + l);
      cf[1][i] = __ldg(p.tab + TB_P2 + (pi ? i : 4 + i) * 32 + l);
      G[i] = __ldg(p.tab + TB_P2 + (8 + i) * 32 + l);
    }
    const uint32_t* zin = sc->z1 + (size_t)R * 5120;
    if (wp == 10) {
      const uint32_t* zu = upin(zin);
      if (elect()) mbar_expect(full0 + 8 * B_Z1, 20480);
      wait_cnt(&sc->cnt[C_Z1 + 32 * (pi >> 2)], 128 * ep);
      if (elect()) {
        bulk_ld(sbase + O_P2, zu, 20480, full0 + 8 * B_Z1);
        TS(12);
      }
      __syncwarp();
    }
    mbar_wait(full0 + 8 * B_FLT, 0);
    CK(9);
    float wn[16], wc[16];
#pragma unroll 1
    for (int ln = nl - 1; ln >= 0; ln--) {
      const int col = col0 + wp + 12 * ln, k2 = (57 * col) & 63;
      const bool cj = k2 > 32 || (k2 == 32 && col != 288);
      const float nr = ((col & 31) == 0 && col != 0 && col != 288 ? 0.5f : 1.0f) / ((float)S_ * D_), ni = cj ? -nr : nr;
#pragma unroll
      for (int i = 0; i < 16; i++) wn[i] = wc[i];
#pragma unroll
      for (int cl = 0; cl < 2; cl++) {
        const int v = cl ^ (cj && pi), e = ((v ? xv : xu) & 15) + wp + 12 * ln, sh = e < 32 ? 6 : 5;
        const uint32_t base = sbase + O_RAW + v * 12288 + (e < 32 ? 2 * e : 8192 - 64 + 2 * e), msk = e < 32 ? 0x30 : 0x10;
        const int dm = v ? (cj || pi ? -1 : 0) : 0;
#pragma unroll
        for (int tt = 0; tt < 4; tt++) {
          const int kc = g + 64 * (tt >> 1) + 16 * t + 8 * (tt & 1);
          uint32_t a = base + ((((cj ? -kc : kc) + dm) & 127) << sh);
          a ^= (a >> 3) & msk;
          wc[4 * tt + 2 * cl] = lds_bf(a) * nr; wc[4 * tt + 2 * cl + 1] = lds_bf(a + 24576) * ni;
        }
      }
    }
    const float al = __uint_as_float(pin((pi ? 0x3f800000u : 0u) + (l >> 5)));
    const uint32_t tagv = pin(tag1 + (l >> 5));
    CK(10);
    uint32_t off = pin(l * 160 + ((wp ^ (g & 3)) << 3));
    uint32_t offo = pin(sbase + O_P2 + 20480 + off - 64 * l), po = 3072;
    unsigned* hz2 = pin(&sc->cnt[C_Z2]);
    const uint32_t do2 = pin(12288 - 32 * l);
    const CUtensorMap* mz2 = upin(&maps.z2[wp == 0]);
    const uint32_t sz2 = upin(sbase + O_P2 + 20480 + (wp ? 0 : 12288)), cz2 = upin(40 * R + (wp ? 0 : 24));
    mbar_wait(full0 + 8 * B_Z1, 0);
    CK(11);
    if (tid == 0) TS(8);
    if (wg == 2) load_wm(72 + cta);
    uint2 v[4], v2[4];
    const uint32_t o2 = nl > 1 ? 96 : 0;
#pragma unroll
    for (int i = 0; i < 4; i++) { v[i] = lds2(sbase + O_P2 + off + i * 5120); v2[i] = lds2(sbase + O_P2 + off + o2 + i * 5120); }
    auto bad2 = [&]() {
      return any(or3(or3(diff2(v[0].x, v[1].x, tagv), diff2(v[2].x, v[3].x, tagv), diff2(v2[0].x, v2[1].x, tagv)), diff2(v2[2].x, v2[3].x, tagv), 0) & 1);
    };
    if (__builtin_expect(bad2() && nl, 0)) {
      FAILCNT(0);
      int it = 0;
      do {
#pragma unroll
        for (int i = 0; i < 4; i++) {
          v[i] = ld_rlx2(reinterpret_cast<const uint8_t*>(zin) + off + i * 5120);
          v2[i] = ld_rlx2(reinterpret_cast<const uint8_t*>(zin) + off + o2 + i * 5120);
        }
      } while (bad2() && ++it < SPIN_MAX);
    }
#pragma unroll 1
    for (int ln = 0; ln < nl; ln++, offo += do2, po = 2048) {
      float d[4][4];
      uint32_t A[8];
#pragma unroll
      for (int h = 0; h < 2; h++) {
        mma16<false>(d[2 * h], cf[0][0].x, cf[0][0].y, cf[0][0].z, cf[0][0].w, v[h].x, v[2 + h].x);
        mma16<false>(d[2 * h + 1], cf[1][0].x, cf[1][0].y, cf[1][0].z, cf[1][0].w, v[h].y, v[2 + h].y);
      }
      if (ln) { fence_async_smem(); bar_arrive(15, NTHR); }
#pragma unroll
      for (int h = 0; h < 2; h++)
#pragma unroll
        for (int L = 0; L < 2; L++) {
          const uint4 tw = cf[L][2 + h];
          const float* z = d[2 * h + L];
          const float2 z0 = cmul(make_float2(z[0], z[2]), make_float2(__uint_as_float(tw.x), __uint_as_float(tw.y)));
          const float2 z1 = cmul(make_float2(z[1], z[3]), make_float2(__uint_as_float(tw.z), __uint_as_float(tw.w)));
          A[4 * h + L] = pack_bf16(z0.x, z0.y); A[4 * h + 2 + L] = pack_bf16(z1.x, z1.y);
        }
#pragma unroll
      for (int tt = 0; tt < 4; tt++) {
        mma16<false>(d[tt], A[0], A[1], A[2], A[3], G[tt].x, G[tt].y);
        mma16<true>(d[tt], A[4], A[5], A[6], A[7], G[tt].z, G[tt].w);
      }
#pragma unroll
      for (int tt = 0; tt < 4; tt++) {
        const float ar = d[tt][0], aj = d[tt][1], br = d[tt][2], bj = d[tt][3];
        const float2 y1 = cmul(make_float2(fmaf(-al, bj, ar), fmaf(al, br, aj)), make_float2(wc[4 * tt], wc[4 * tt + 1]));
        const float2 y2 = cmul(make_float2(fmaf(al, ar, bj), fmaf(al, aj, -br)), make_float2(wc[4 * tt + 2], wc[4 * tt + 3]));
        A[2 * tt] = pack_bf16(fmaf(al, y2.x, y1.x), fmaf(-al, y2.y, -y1.y));
        A[2 * tt + 1] = pack_bf16(fmaf(al, y1.y, -y2.y), fmaf(al, y1.x, -y2.x));
      }
#pragma unroll
      for (int i = 0; i < 16; i++) wc[i] = wn[i];
#pragma unroll
      for (int i = 0; i < 4; i++) v[i] = v2[i];
#pragma unroll
      for (int tt = 0; tt < 4; tt++) {
        mma16<false>(d[tt], A[0], A[1], A[2], A[3], G[tt].x, G[tt].y);
        mma16<true>(d[tt], A[4], A[5], A[6], A[7], G[tt].z, G[tt].w);
      }
#pragma unroll
      for (int h = 0; h < 2; h++)
#pragma unroll
        for (int L = 0; L < 2; L++) {
          const uint4 tw = cf[L][2 + h];
          const float2 z0 = cmul(make_float2(d[2 * h][2 * L], d[2 * h][2 * L + 1]), make_float2(__uint_as_float(tw.x), __uint_as_float(tw.y)));
          const float2 z1 = cmul(make_float2(d[2 * h + 1][2 * L], d[2 * h + 1][2 * L + 1]), make_float2(__uint_as_float(tw.z), __uint_as_float(tw.w)));
          A[4 * h + 2 * L] = movm(pack_bf16(z0.x, z1.x)); A[4 * h + 2 * L + 1] = movm(pack_bf16(z0.y, z1.y));
        }
#pragma unroll
      for (int h = 0; h < 2; h++) {
        mma16<false>(d[0], cf[0][1].x, cf[0][1].y, cf[0][1].z, cf[0][1].w, A[4 * h], A[4 * h + 1]);
        mma16<false>(d[1], cf[1][1].x, cf[1][1].y, cf[1][1].z, cf[1][1].w, A[4 * h + 2], A[4 * h + 3]);
#pragma unroll
        for (int e = 0; e < 2; e++)
          sts2(offo + (2 * h + e) * po, set_tag(pack_bf16(d[0][e], d[0][2 + e]), tagv), pack_bf16(d[1][e], d[1][2 + e]));
      }
      CK(12 + ln);
    }
    fence_async_smem();
    if (nl < 2 && wp != 8) bar_arrive(15, NTHR);
    if (wp & 7) { if (wg < 2) bar_arrive(6, 256); }
    else {
      if (wp) bar_sync(15, NTHR); else bar_sync(6, 256);
      if (elect()) {
        tma_st2d(mz2, sz2, cz2, 0);
        HW();
        if (wp == 0) { red_add(hz2, 1); TS(9); }
      }
      __syncwarp();
    }
  }
  if (wg == 2) {
#pragma unroll 1
    for (int u = 72 + cta, k = 0; u < 216; u += NCTA, k ^= 1) {
      if (R < 0) { fence_async_smem(); bar_sync(4, 128); load_wm(u); }
      mod_unit(sc, u, t128, sbase + O_NRM, full0 + 8 * B_WM, k, red + 256 - 256 * k, tag16);
    }
    fence_async_smem();
    CK(13);
  }

  const int grp = cta / 11, m1 = cta - 11 * grp;
  const bool helper = (m1 & 3) == 3;
  const int f1 = 384 * grp + (helper ? 192 : 128) * (m1 >> 2);
  const int d1 = 160 * (m1 & 3), flip = m1 >= 7;
  const int a1bytes = helper ? 24576 : 16384;
  auto load_a1 = [&](int st, int kb) {
    mbar_expect(full0 + 8 * st, a1bytes);
    tma4d_ef(sbase + st * STAGE, helper ? &maps.w1b : &maps.w1a, 4 * (kb >> 3), 16 * (kb & 7), f1 >> 6, full0 + 8 * st);
  };

  if (rows) {
#pragma unroll
    for (int kk = 0; kk < 4; kk++) af[kk] = __ldg(p.tab + TB_E + kk * 128 + t128);
    const uint4 c0 = lds4(sbase + O_ST + tid * 16), c1 = lds4(sbase + O_ST + 6144 + tid * 16);
    const uint2 c2 = lds2(sbase + O_ST + 12288 + tid * 8);
    const uint32_t tb[4] = {c0.x, c0.y, c0.z, c0.w}, sy[6] = {c1.x, c1.y, c1.z, c1.w, c2.x, c2.y};
    const uint32_t l8 = pin(8 * l), syl = pin(sbase + O_Y + wp * 2336 + 8 * l);
    const uint32_t sh3 = pin(sbase + O_B3 + (wp >> 1) * 4608 + (l >> 4) * 256 + (wp & 1) * 128 + ((((l >> 2) ^ (2 * cta + (wp & 1))) & 3) << 4) + (l & 3) * 4);
    const bool htag = (((sh3 >> 2) ^ (2 * cta + (wp & 1))) & 7) == 0;
    const uint32_t ham = pin(htag ? ~1u : ~0u), hom = pin(htag ? tag1 : 0u);
    const int slot = 4 * (cta >> 4) + ((cta >> 1) & 3) + 32 * (2 * ((cta >> 3) & 1) + (cta & 1));
    const uint32_t* zin = sc->z2 + (size_t)slot * 4800;
    if (wg == 2) {
      {
        uint4 v[4];
        const int i3 = min(t128 + 384, 431);
        int it = 0;
        while (true) {
          uint32_t bad = 0;
#pragma unroll
          for (int k = 0; k < 4; k++) v[k] = ld_rlx4(sc->mod + 4 * (k < 3 ? t128 + 128 * k : i3));
#pragma unroll
          for (int k = 0; k < 4; k++) {
            v[k].x ^= tag16; v[k].y ^= tag16; v[k].z ^= tag16; v[k].w ^= tag16;
            bad |= v[k].x | v[k].y | v[k].z | v[k].w;
          }
          if (!any(bad & 0xffffu) || ++it > SPIN_MAX) break;
        }
#pragma unroll
        for (int k = 0; k < 4; k++) sts4(sbase + O_MOD + 16 * (k < 3 ? t128 + 128 * k : i3), v[k].x, v[k].y, v[k].z, v[k].w);
      }
      CK(14);
      bar_sync(10, NTHR);
      mbar_wait(full0 + 8 * B_Z2, 0);
      if (elect()) {
        load_a1(wp - 8, wp - 8);
        if (wp > 8 && wp - 8 < NG1) prefetch_l2(reinterpret_cast<const uint8_t*>(p.w1) + (size_t)(128 * (4 * ((wp - 8) >> 1) + (cta >> 5)) + 64 * (wp & 1) + 2 * (cta & 31)) * (2 * F_), 4 * F_);
      }
      __syncwarp();
    } else {
      const uint4 e0 = lds4(sbase + O_ST + 15360 + tid * 16), e1 = lds4(sbase + O_ST + 19456 + tid * 16), e2 = lds4(sbase + O_ST + 23552 + tid * 16);
      const uint32_t lo[9] = {e0.x, e0.y, e0.z, e0.w, e1.x, e1.y, e1.z, e1.w, e2.x}, lx = e2.y, sb3 = e2.z;
      bar_arrive(10, NTHR);
      CK(14);
      if (wp == 1) {
        const uint32_t* zu = upin(zin);
        if (elect()) mbar_expect(full0 + 8 * B_Z2, 19200);
        wait_cnt(&sc->cnt[C_Z2], 120 * ep);
        if (elect()) {
          bulk_ld(sbase + O_IN, zu, 19200, full0 + 8 * B_Z2);
          TS(14);
        }
        __syncwarp();
      }
      mbar_wait(full0 + 8 * B_Z2, 0);
      CK(15);
      if (tid == 0) TS(11);
      uint2 v[10];
#pragma unroll
      for (int k1 = 0; k1 < 10; k1++) v[k1] = lds2(k1 < 9 ? lo[k1] : lx);
      auto bad3 = [&]() {
        return any(or3(or3(diff2(v[0].x, v[1].x, tag1), diff2(v[2].x, v[3].x, tag1), diff2(v[4].x, v[5].x, tag1)), diff2(v[6].x, v[7].x, tag1), diff2(v[8].x, v[9].x, tag1)) & 1);
      };
      if (__builtin_expect(bad3(), 0)) {
        FAILCNT(1);
        int it = 0;
        do {
#pragma unroll
          for (int k1 = 0; k1 < 10; k1++) v[k1] = ld_rlx2(reinterpret_cast<const uint8_t*>(zin) + ((k1 < 9 ? lo[k1] : lx) - (sbase + O_IN)));
        } while (bad3() && ++it < SPIN_MAX);
      }
      float2 za[9], zb[9];
#pragma unroll
      for (int i = 0; i < 9; i++) { za[i] = make_float2(bf_lo(v[i].x), bf_hi(v[i].x)); zb[i] = make_float2(bf_lo(v[i].y), bf_hi(v[i].y)); }
      if (kap == 0) {
#pragma unroll
        for (int k = 1; k < 5; k++) {
          float2 a = za[k], b = za[9 - k];
          za[k] = make_float2(a.x - b.y, a.y + b.x); za[9 - k] = make_float2(a.x + b.y, b.x - a.y);
          a = zb[k]; b = zb[9 - k];
          zb[k] = make_float2(a.x - b.y, a.y + b.x); zb[9 - k] = make_float2(a.x + b.y, b.x - a.y);
        }
        za[0].y = bf_lo(v[9].x); zb[0].y = bf_lo(v[9].y);
      }
      __syncwarp();
      dft9(za); dft9(zb);
#pragma unroll
      for (int n = 0; n < 8; n += 2) {
        const int i0 = (9 - n) % 9, i1 = 8 - n;
        stmatrix4(sb3 + n * 2048, pack_bf16(za[i0].x, zb[i0].x), pack_bf16(za[i0].y, zb[i0].y), pack_bf16(za[i1].x, zb[i1].x), pack_bf16(za[i1].y, zb[i1].y));
      }
      stmatrix2(sb3 + 8 * 2048, pack_bf16(za[1].x, zb[1].x), pack_bf16(za[1].y, zb[1].y));
      fence_async_smem();
    }
    CK(16);
    __syncthreads();
    CK(17);
    float acc[24];
    const uint32_t db = (((sbase + O_B3 + wg * 6144) & 0x3FFFF) >> 4) | ((128 >> 4) << 16);
    wg_fence();
#pragma unroll
    for (int kk = 0; kk < 4; kk++) wgmma_rs_48(acc, af[kk].x, af[kk].y, af[kk].z, af[kk].w, db + kk * 16, 1024 >> 4, kk);
    wg_commit();
    uint32_t ga[9];
    uint2 sh[9], sw[9];
    if (wg < 2) {
#pragma unroll
      for (int i = 0; i < 9; i++) {
        const uint2 v = lds2(l8 + sbase + O_MOD + 256 * i);
        ga[i] = __byte_perm(v.x, v.y, 0x7632);
        sh[i] = lds2(l8 + sbase + O_MOD + 4 * D_ + 256 * i);
        sw[i] = lds2(l8 + sbase + O_MOD + 8 * D_ + 256 * i);
      }
    }
    wg_wait<0>();
    reg_fence(acc);
    CK(18);
#pragma unroll
    for (int i = 0; i < 3; i++) {
      const float* a = &acc[8 * i];
      const uint32_t a0 = pack_bf16(a[0], a[1]), a1 = pack_bf16(a[2], a[3]), a2 = pack_bf16(a[4], a[5]), a3 = pack_bf16(a[6], a[7]);
#pragma unroll
      for (int jh = 0; jh < 2; jh++) {
        float y[4];
        mma16<false>(y, a0, a1, a2, a3, tb[2 * jh], tb[2 * jh + 1]);
        sts(sy[2 * i] + jh * (4 * 584 * 4), pack_bf16(y[0], y[1]));
        sts(sy[2 * i + 1] + jh * (4 * 584 * 4), pack_bf16(y[2], y[3]));
      }
    }
    CK(19);
    if (wg == 2) bar_arrive(7, NTHR);
    else {
      bar_sync(7, NTHR);
      CK(20);
      float a[18], b[18];
#pragma unroll
      for (int i = 0; i < 9; i++) {
        const uint2 y = lds2(syl + 256 * i);
        xr[i] = hfma2(ga[i], __byte_perm(y.x, y.y, 0x5410), xr[i]);
        xr[9 + i] = hfma2(ga[i], __byte_perm(y.x, y.y, 0x7632), xr[9 + i]);
        a[2 * i] = bf_lo(xr[i]); a[2 * i + 1] = bf_hi(xr[i]); b[2 * i] = bf_lo(xr[9 + i]); b[2 * i + 1] = bf_hi(xr[9 + i]);
      }
      float oa, ra, ob, rb;
      ln_stats2(a, b, 1.0f, oa, ra, ob, rb);
      CK(21);
#pragma unroll
      for (int i = 0; i < 9; i++) {
        const float c0 = __uint_as_float(sw[i].x), c1 = __uint_as_float(sw[i].y), s0 = __uint_as_float(sh[i].x), s1 = __uint_as_float(sh[i].y);
        a[2 * i] = fmaf(fmaf(a[2 * i], ra, oa), c0, s0); a[2 * i + 1] = fmaf(fmaf(a[2 * i + 1], ra, oa), c1, s1);
        b[2 * i] = fmaf(fmaf(b[2 * i], rb, ob), c0, s0); b[2 * i + 1] = fmaf(fmaf(b[2 * i + 1], rb, ob), c1, s1);
      }
      ln_stats2(a, b, 0.5f, oa, ra, ob, rb);
      CK(22);
#pragma unroll
      for (int i = 0; i < 9; i++) {
        sts(sh3 + i * 512, and_or(pack_bf16(fmaf(a[2 * i], ra, oa), fmaf(a[2 * i + 1], ra, oa)), ham, hom));
        sts(sh3 + i * 512 + 64, and_or(pack_bf16(fmaf(b[2 * i], rb, ob), fmaf(b[2 * i + 1], rb, ob)), ham, hom));
      }
      fence_async_smem();
      if (wp < 2 * H3G) bar_arrive(8, 32 + 64 * H3G); else bar_arrive(9, 288 - 64 * H3G);
      CK(23);
    }
  } else __syncthreads();

  const bool g2 = cta < 130 && (cta >> 1) != 56;
  const int z2 = cta < 112 ? cta : cta - 2, r = z2 >> 6;
  const int s2 = 128 * ((z2 >> 2) & 15), d2 = 144 * (z2 & 3);
  constexpr int XST = (33 + 36 - JSK - 1) % NST;
  constexpr int ST0 = (32 - JSK - 1) % NST, ST1 = 31 % NST;

  if (wg == 2) {
    asm volatile("setmaxnreg.dec.sync.aligned.u32 40;");
    auto load_b = [&](bool second, int i, int st) {
      const uint32_t lb = full0 + 8 * (B_LAND + st), bytes = second ? 18432 : STAGE - a1bytes;
      mbar_expect(lb, bytes);
      bulk_ld(sbase + (second ? st * STAGE2 + 16384 : st * STAGE + a1bytes),
              second ? sc->u + ((size_t)(36 * r + kb2_order(i)) * D_ + d2) * 128 : sc->h3 + ((size_t)(i * 18 + (d1 >> 5)) << 12), bytes, lb);
    };
    if (wp == 8) {
      int st = rows ? 4 : 0, ph = 1;
#pragma unroll 1
      for (int kb = st; kb < 32; kb++) {
        if (rows && (kb >> 1) == 2) mbar_wait(full0 + 8 * (B_S4 - 4 + kb), 0);
        mbar_wait(empty0 + 8 * st, ph);
        if (elect()) {
          load_a1(st, kb);
          if (kb >= PF2K && kb < PF2K + PF2 && g2)
            prefetch_l2(reinterpret_cast<const uint8_t*>(p.w2) + (size_t)(36 * r + kb2_order(kb - PF2K)) * 262144 + (z2 & 63) * 4096, 4096);
        }
        __syncwarp();
        ring_next<false>(st, ph);
      }
      if (g2) {
        st++;
#pragma unroll 1
        for (int i = 0; i < 36; i++) {
          if (i == HOLDA) mbar_wait(full0 + 8 * B_GO, 0);
          mbar_wait(empty0 + 8 * st, ph);
          if (elect()) {
            mbar_expect(full0 + 8 * st, 16384);
            tma3d_ef(sbase + st * STAGE2, &maps.w2, 64 * (36 * r + kb2_order(i)), s2 >> 6, full0 + 8 * st);
          }
          __syncwarp();
          ring_next<true>(st, ph);
        }
      }
    } else if (wp >= 10) {
      const int sw = wp - 10;
      if (rows) {
        const CUtensorMap* mp = upin(&maps.h3[sw]);
        const uint32_t src = upin(sbase + O_B3 + sw * (H3G * 4608)), c0 = upin(64 * (cta & 15)), c1 = upin(18 * (cta >> 4)), c2 = upin(H3G * sw);
        unsigned* flag = pin(&sc->cnt[C_H3 + (cta >> 4) + 8 * sw]);
        bar_sync(8 + sw, sw ? 288 - 64 * H3G : 32 + 64 * H3G);
        if (sw) mbar_wait(full0 + 8 * H3W, 0);
        if (elect()) {
          tma_st3d(mp, src, c0, c1, c2);
          mbar_arrive(full0 + 8 * B_S4);
          bulk_commit_wait();
          red_add(flag, 1);
          mbar_arrive(full0 + 8 * B_S5);
          TS(sw ? 24 : 13);
        }
        __syncwarp();
      }
      if (sw) {
        if (rows) {
          mbar_wait(full0 + 8 * B_S5, 0);
          if (elect()) { asm volatile("fence.acq_rel.gpu;" ::: "memory"); red_add(&sc->cnt[C_X + 64], 1); }
          __syncwarp();
        }
        if (g2) {
          uint2 v[3];
          int it = 0;
          do {
#pragma unroll
            for (int i = 0; i < 3; i++) v[i] = ld_rlx2(sc->mod + 3 * D_ + d2 + 2 * min(l + 32 * i, 71));
          } while (any(or3(diff2(v[0].x, v[0].y, tag16), diff2(v[1].x, v[1].y, tag16), diff2(v[2].x, v[2].y, tag16)) & 0xffffu) && ++it < SPIN_MAX);
#pragma unroll
          for (int i = 0; i < 3; i++) sts(sbase + O_GB + 4 * min(l + 32 * i, 71), __byte_perm(v[i].x, v[i].y, 0x7632));
          __syncwarp();
        }
        wait_cnt<true>(&sc->cnt[C_X + 64], 128 * ep);
        if (elect()) mbar_arrive(full0 + 8 * B_X);
        __syncwarp();
      }
      uint32_t lph = 0;
      auto check_tiles = [&](bool second, int n, int st, uint32_t o1, uint32_t d2nd) {
        const uint32_t b1 = pin(sbase + o1), b2 = pin(sbase + o1 + d2nd);
        int i = 0, it = 0;
#pragma unroll 1
        do {
          const uint32_t so = st * (second ? STAGE2 : STAGE);
          mbar_wait(full0 + 8 * (B_LAND + st), (lph >> st) & 1);
          lph ^= 1u << st;
          uint32_t v[20];
#pragma unroll
          for (int k = 0; k < 20; k++) if (!second || k < 10 || k >= 12) v[k] = lds(k < 12 ? b1 + so + k * 1024 : b2 + so + (k - 12) * 1024); else v[k] = tag1;
#pragma unroll
          for (int k = 0; k < 10; k++) v[k] = diff2(v[2 * k], v[2 * k + 1], tag1);
          const uint32_t bad = or3(or3(or3(v[0], v[1], v[2]), or3(v[3], v[4], v[5]), v[6]), v[7], or3(v[8], v[9], 0));
          if (__builtin_expect(any(bad & 1) && ++it < SPIN_MAX, 0)) {
            FAILCNT(2 + second);
            fence_async_smem();
            __syncwarp();
            if (elect()) load_b(second, i, st);
            __syncwarp();
            continue;
          }
          if (elect()) mbar_arrive(full0 + 8 * st);
          if (++st == NST) st = 0;
          i++;
        } while (i < n);
      };
      if (!sw) check_tiles(false, NV1, 0, a1bytes + l * 32 + (l >> 2) * 4, helper ? 4096 : 12288);
      const bool first = helper || m1 < W0N;
#pragma unroll 1
      for (int k = sw ? first : !first; k <= sw; k++) {
        const uint32_t stg = sbase + (!k ? ST0 * STAGE : helper ? ST1 * STAGE : O_U1);
        const int kbA = (f1 >> 6) + (helper ? 2 : 1) * (k ^ flip), kbB = helper ? (f1 >> 6) + 1 : kbA;
        uint8_t* const uA = upin(sc->u + ((size_t)kbA * D_ + d1) * 128);
        uint8_t* const uB = upin(sc->u + ((size_t)kbB * D_ + (helper ? d1 : d1 + 96)) * 128);
        unsigned* const fA = pin(&sc->cnt[C_U + kbA]);
        unsigned* const fB = pin(&sc->cnt[C_U + kbB]);
        const bool slow = sw && !helper;
        bar_sync(11 + k, 160);
        if (!slow) { if (elect()) { bulk_st(uA, stg, 96 * 128); TS(k ? 31 : 30); } __syncwarp(); }
        bar_sync(13 + k, 160);
        if (slow) {
          if (g2) mbar_wait(full0 + 8 * B_GO, 0);
          if (first) pause(10 * TRK0);
#pragma unroll 1
          for (int i = 0; i < 20480; i += 2048) {
            if (elect()) bulk_st(uA + i, stg + i, 2048);
            pause(k ? TRKC : TRK0);
          }
        }
        if (elect()) {
          if (helper ? k : !slow) bulk_st(uB, stg + 96 * 128, helper ? 96 * 128 : 64 * 128);
          bulk_commit_wait();
          red_add(fA, 1);
          if (helper && k) red_add(fB, 1);
          if (!k || helper) mbar_arrive(empty0 + 8 * (k ? ST1 : ST0));
          TS(k ? 23 : 17);
          mbar_arrive(full0 + 8 * B_S5);
        }
        __syncwarp();
      }
      if (sw) {
        mbar_wait(full0 + 8 * B_S5, rows);
        if (elect()) { asm volatile("fence.acq_rel.gpu;" ::: "memory"); red_add(&sc->cnt[C_X], 1); }
        __syncwarp();
      }
      if (g2) {
        if (!sw) check_tiles(true, NV2, 3, 16384 + l * 32 + (4 * (g & 1) + (g >> 1)) * 4, 10240);
        else {
          wait_cnt<true>(&sc->cnt[C_X], NCTA * ep);
          if (elect()) {
            mbar_arrive(full0 + 8 * B_X);
            if (cta == 0) sc->cnt[C_EP] = ep;
          }
          __syncwarp();
        }
      }
      __syncwarp();
    } else {
      uint64_t ready = 0;
      int st = 0, ph = 1;
#pragma unroll 1
      for (int kb = 0; kb < 32; kb++) {
        const uint8_t* src = upin(sc->h3 + ((size_t)(kb * 18 + (d1 >> 5)) << 12));
        const uint32_t dst = upin(sbase + st * STAGE + a1bytes), lb = full0 + 8 * ((kb < NV1 ? B_LAND : 0) + st);
        if (kb == NV1) { mbar_wait(full0 + 8 * B_X, 0); fence_async_glb(); ready = ~0ull; }
        if (rows && (kb >> 1) == 2) mbar_wait(full0 + 8 * (B_S4 - 4 + kb), 0);
        mbar_wait(empty0 + 8 * st, ph);
        if (elect()) mbar_expect(lb, STAGE - a1bytes);
        wait_flags(sc->cnt + C_H3, 32, (kb & 7) + (kb < 8 * H3G ? 0 : 8), 16 * ep, ready);
        if (elect()) bulk_ld(dst, src, STAGE - a1bytes, lb);
        ring_next<false>(st, ph);
      }
      if (g2) {
        ready = 0;
        st++;
#pragma unroll 1
        for (int i = 0; i < 36; i++) {
          const int kb = kb2_order(i);
          const uint8_t* src = upin(sc->u + ((size_t)(36 * r + kb) * D_ + d2) * 128);
          const uint32_t dst = upin(sbase + st * STAGE2 + 16384), lb = full0 + 8 * ((i < NV2 ? B_LAND : 0) + st);
          if (i == NV2) { mbar_wait(full0 + 8 * B_X, 1); fence_async_glb(); ready = ~0ull; }
          mbar_wait(empty0 + 8 * st, ph);
          if (elect()) mbar_expect(lb, 18432);
          wait_flags(sc->cnt + C_U + 36 * r, 36, kb, 4 * ep, ready);
          if (elect()) {
            bulk_ld(dst, src, 18432, lb);
            if (i == GOAT) mbar_arrive(full0 + 8 * B_GO);
          }
          ring_next<true>(st, ph);
        }
      }
    }
  } else {
    asm volatile("setmaxnreg.inc.sync.aligned.u32 232;");
    const int wgu = wg;
    constexpr uint32_t sb4 = sbase >> 4;
    const int w = wp & 3;
    Ring rg = {0, 0};
    uint32_t* const x1p = p.out + (size_t)(cta + 256 * wp) * 288 + l;
    const uint32_t ad = pin(sbase + (!wg ? ST0 * STAGE : helper ? ST1 * STAGE : O_U1) + (8 * (l >> 4) + (l & 7)) * 128 + (((2 * w + ((l >> 3) & 1)) ^ (l & 7)) << 4));
    const uint32_t uam = pin(g == 2 * t ? 0xfffefffeu : ~0u), uom = pin(g == 2 * t ? tag1 * 0x10001u : 0u);
    float acc[96];
    constexpr uint32_t LA = (8192 >> 4) << 16, LB = (4096 >> 4) << 16;
    {
      const int fa = f1 + (helper ? 128 : 64) * (wg ^ flip) + 16 * w + g, fb = helper ? f1 + 64 + 16 * w + g : fa;
      const float a0 = 0.5f * __bfloat162float(p.b1[fa]), a1 = 0.5f * __bfloat162float(p.b1[fa + 8]);
      const float b0 = 0.5f * __bfloat162float(p.b1[fb]), b1 = 0.5f * __bfloat162float(p.b1[fb + 8]);
#pragma unroll
      for (int i = 0; i < 96; i++) acc[i] = i < 48 ? ((i & 2) ? a1 : a0) : ((i & 2) ? b1 : b0);
      reg_fence(acc);
    }
    if (!helper) gemm_main<0>(acc, sb4 + (wgu ^ flip) * 512 + LA, 0, sb4 + 1024 + LB, wgu, rg, x1p, xr);
    else {
      float ac2[96];
#pragma unroll
      for (int i = 0; i < 96; i++) asm volatile("mov.b32 %0, %1;" : "=f"(ac2[i]) : "f"(acc[i]));
      gemm_main<1>(ac2, sb4 + (wgu ^ flip) * 1024 + LA, sb4 + 512 + LA, sb4 + 1536 + LB, wgu, rg, x1p, xr);
#pragma unroll
      for (int i = 0; i < 96; i++) asm volatile("mov.b32 %0, %1;" : "=f"(acc[i]) : "f"(ac2[i]));
    }
    if (t128 == 0) TS(wg ? 16 : 6);
    {
      float tp[2] = {0.f, 0.f};
#pragma unroll
      for (int j = 0; j < 12; j++) {
        const float* a = &acc[8 * j];
        const float k3 = j < 2 ? GK3 : fmaf(tp[j & 1], 0.0f, GK3);
        float o[8];
#pragma unroll
        for (int e = 0; e < 8; e++) {
          float z = a[e] * fmaf(a[e] * k3, a[e], GK1);
          asm("tanh.approx.f32 %0, %0;" : "+f"(z));
          if (e == GDEP) tp[j & 1] = z;
          o[e] = fmaf(a[e], z, a[e]);
        }
        stmatrix4t(ad + j * 2048, and_or(pack_bf16(o[0], o[1]), uam, uom), pack_bf16(o[2], o[3]), and_or(pack_bf16(o[4], o[5]), uam, uom), pack_bf16(o[6], o[7]));
        if (j == 5) {
          fence_async_smem();
          bar_arrive(11 + wgu, 160);
        }
        if ((j == 5 && helper && !wgu) || (j == 9 && !helper)) break;
      }
      fence_async_smem();
      bar_arrive(13 + wgu, 160);
      if (t128 == 0) TS(wg ? 29 : 28);
    }
    if (g2) {
      const int mb = wgu ^ r;
      uint32_t gb[18];
      {
        float a0 = 0.f, a1 = 0.f;
        if (wgu) { a0 = __bfloat162float(p.b2[s2 + 64 * mb + 16 * w + g]); a1 = __bfloat162float(p.b2[s2 + 64 * mb + 16 * w + 8 + g]); }
        const uint32_t t4 = pin(4 * t);
#pragma unroll
        for (int i = 0; i < 18; i++) gb[i] = lds(t4 + sbase + O_GB + 16 * i);
#pragma unroll
        for (int i = 0; i < 72; i++) acc[i] = (i & 2) ? a1 : a0;
      }
      const uint32_t xb = sbase + (wg ? XST * STAGE2 : O_U1) + w * 4864;
      const uint32_t xa = pin(xb + (l & 15) * 304 + (l >> 4) * 16), xl = pin(xb + (l >> 3) * 304 + (l & 7) * 16), xm = pin(xb + (l >> 1) * 304 + 256 + (l & 1) * 16);
      uint32_t* const ob = p.out + (size_t)(s2 + 64 * mb + 16 * w) * 288 + (d2 >> 1);
      uint32_t* const ol = pin(ob + (l >> 3) * 288 + (l & 7) * 4);
      uint32_t* const om = pin(ob + (l >> 1) * 288 + 64 + (l & 1) * 4);
      rg.st++;
      gemm_main<3>(acc, sb4 + mb * 512 + LA, 0, sb4 + 1024 + (1 << 16), wgu, rg, x1p, xr);
      if (t128 == 0) TS(wg ? 20 : 19);
#pragma unroll
      for (int j = 0; j < 9; j++) {
        const float* a = &acc[8 * j];
        stmatrix4(xa + j * 32, hmul2(gb[2 * j], pack_bf16(a[0], a[1])), hmul2(gb[2 * j], pack_bf16(a[2], a[3])),
                  hmul2(gb[2 * j + 1], pack_bf16(a[4], a[5])), hmul2(gb[2 * j + 1], pack_bf16(a[6], a[7])));
        if (j == 3 || j == 8) {
          __syncwarp();
          uint4 v[5];
#pragma unroll
          for (int i = 0; i < 4; i++) v[i] = lds4(xl + i * 1216 + (j >> 3) * 128);
          if (j == 8) v[4] = lds4(xm);
#pragma unroll
          for (int i = 0; i < 4; i++) red_bf16x8(ol + i * 1152 + (j >> 3) * 32, v[i]);
          if (j == 8) red_bf16x8(om, v[4]);
        }
      }
      if (t128 == 0) TS(wg ? 7 : 21);
      __syncwarp();
    }
  }
}

typedef CUresult (*EncodeFn)(CUtensorMap*, CUtensorMapDataType, cuuint32_t, void*, const cuuint64_t*, const cuuint64_t*, const cuuint32_t*,
                             const cuuint32_t*, CUtensorMapInterleave, CUtensorMapSwizzle, CUtensorMapL2promotion, CUtensorMapFloatOOBfill);

struct Dim { cuuint64_t n, stride; cuuint32_t box; };
template <int RANK>
void make_map(EncodeFn enc, CUtensorMap* m, bool words, int swz, const void* ptr, const Dim (&d)[RANK]) {
  cuuint64_t gd[RANK], gs[RANK];
  cuuint32_t bx[RANK], es[RANK];
  for (int i = 0; i < RANK; i++) { gd[i] = d[i].n; gs[i] = d[i].stride; bx[i] = d[i].box; es[i] = 1; }
  enc(m, words ? CU_TENSOR_MAP_DATA_TYPE_UINT32 : CU_TENSOR_MAP_DATA_TYPE_BFLOAT16, RANK, const_cast<void*>(ptr), gd, gs + 1, bx, es,
      CU_TENSOR_MAP_INTERLEAVE_NONE, static_cast<CUtensorMapSwizzle>(swz),
      swz == 3 ? CU_TENSOR_MAP_L2_PROMOTION_L2_256B : CU_TENSOR_MAP_L2_PROMOTION_NONE, CU_TENSOR_MAP_FLOAT_OOB_FILL_NONE);
}

}

extern "C" void kernel_launch(void* const* d_in, const int* in_sizes, int n_in, void* d_out, int out_size) {
  (void)in_sizes; (void)n_in; (void)out_size;
  static EncodeFn enc = nullptr;
  static void *sptr = nullptr, *tptr = nullptr;
  if (!enc) {
    void* f = nullptr; cudaDriverEntryPointQueryResult qr;
    cudaGetDriverEntryPoint("cuTensorMapEncodeTiled", &f, cudaEnableDefault, &qr);
    enc = reinterpret_cast<EncodeFn>(f);
    cudaFuncSetAttribute(fused_kernel, cudaFuncAttributeMaxDynamicSharedMemorySize, SMEM_BYTES);
    cudaGetSymbolAddress(&sptr, g_s);
    cudaGetSymbolAddress(&tptr, T_TAB);
  }
  Params p;
  p.x = (const __nv_bfloat16*)d_in[0]; p.wr = (const __nv_bfloat16*)d_in[1]; p.wi = (const __nv_bfloat16*)d_in[2];
  p.b1 = (const __nv_bfloat16*)d_in[5]; p.b2 = (const __nv_bfloat16*)d_in[7];
  p.c = (const __nv_bfloat16*)d_in[8]; p.wmod = (const __nv_bfloat16*)d_in[9];
  p.w1 = (const __nv_bfloat16*)d_in[4]; p.w2 = (const __nv_bfloat16*)d_in[6];
  p.out = static_cast<uint32_t*>(d_out); p.s = static_cast<Scratch*>(sptr); p.tab = static_cast<const uint4*>(tptr);
  Maps maps;
  make_map<4>(enc, &maps.w1a, false, 3, p.w1, {{64, 0, 64}, {16, 128 * 2 * F_, 4}, {128, 2 * F_, 16}, {72, 128, 2}});
  make_map<4>(enc, &maps.w1b, false, 3, p.w1, {{64, 0, 64}, {16, 128 * 2 * F_, 4}, {128, 2 * F_, 16}, {72, 128, 3}});
  make_map<3>(enc, &maps.w2, false, 3, p.w2, {{64, 0, 64}, {F_, 2 * S_, 64}, {32, 128, 2}});
  make_map<2>(enc, &maps.z1, true, 0, p.s->z1, {{5120, 0, 40}, {120, 20480, 60}});
  for (int i = 0; i < 2; i++) make_map<2>(enc, &maps.z2[i], true, 0, p.s->z2, {{4800, 0, i ? 16u : 24u}, {128, 19200, 128}});
  for (int i = 0; i < 4; i++) make_map<2>(enc, &maps.wf[i], false, 2 - (i & 1), (i & 2) ? p.wi : p.wr, {{16 * DF_, 0, (i & 1) ? 16u : 32u}, {128, 32 * DF_, 128}});
  make_map<2>(enc, &maps.wm, false, 1, p.wmod, {{6 * D_, 0, 16}, {D_, 12 * D_, 192}});
  for (int i = 0; i < 2; i++) make_map<3>(enc, &maps.h3[i], true, 0, p.s->h3, {{1024, 0, 64}, {144, 4096, 18}, {4, 144 * 4096, i ? 4u - H3G : H3G}});
  fused_kernel<<<NCTA, NTHR, SMEM_BYTES, cudaStreamPerThread>>>(p, maps);
}
```

```cpp
#include <cuda_runtime.h>
#include <cuda_bf16.h>
#include <cuda.h>
#include <stdint.h>

namespace {

constexpr int S_ = 2048, D_ = 576, DF_ = 289, F_ = 4608;
constexpr int NCTA = 132, NTHR = 384;
constexpr int STAGE = 36864, NST = 6;
constexpr int STAGE2 = 34816, O_U1 = NST * STAGE2, O_GB = O_U1 + 20480, SMEM_BYTES = 232448;
constexpr uint32_t sbase = 1024, red = sbase + NST * STAGE, full0 = sbase + SMEM_BYTES - 256, empty0 = full0 + 8 * NST;
constexpr int O_NRM = 0, O_B1 = 19456, O_Z1 = 38912, O_P2 = 59392, O_ST = 3 * STAGE;
constexpr int O_RAW = 4 * STAGE;
constexpr int O_IN = 4 * STAGE, O_Y = O_IN + 19456, O_B3 = O_IN + 38912, O_MOD = O_IN + 57344;

__device__ __align__(128) const uint32_t T_TAB[5632] = {
0x3f803f80,0xbf803f80,0x3f803f80,0xbf803f80,0x3f803f80,0xbf803f80,0x3f803f80,0xbf803f80,0x3f803f80,0xbf803f80,0x3f803f80,0xbf803f80,
0x3f803f80,0xbf803f80,0x3f803f80,0xbf803f80,0x3f7f3f80,0xbdc90000,0x3f223f35,0xbf46bf35,0x3f753f7b,0xbe95be48,0x3ef13f0e,0xbf62bf55,
0x3f623f6d,0xbef1bec4,0x3e953ec4,0xbf75bf6d,0x3f463f55,0xbf22bf0e,0x3dc93e48,0xbf7fbf7b,0x3f7b3f80,0xbe480000,0xbe480000,0xbf7bbf80,
0x3f553f6d,0xbf0ebec4,0xbf0ebec4,0xbf55bf6d,0x3f0e3f35,0xbf55bf35,0xbf55bf35,0xbf0ebf35,0x3e483ec4,0xbf7bbf6d,0xbf7bbf6d,0xbe48bec4,
0x3f753f80,0xbe950000,0xbf62bf35,0xbef1bf35,0x3f223f55,0xbf46bf0e,0xbf7fbf7b,0x3dc9be48,0x3dc93ec4,0xbf7fbf6d,0xbf46bf6d,0x3f223ec4,
0xbef1be48,0xbf62bf7b,0xbe95bf0e,0x3f753f55,0x3f6d3f80,0xbec40000,0xbf6dbf80,0x3ec40000,0x3ec43f35,0xbf6dbf35,0xbec4bf35,0x3f6d3f35,
0xbec40000,0xbf6dbf80,0x3ec40000,0x3f6d3f80,0xbf6dbf35,0xbec4bf35,0x3f6d3f35,0x3ec43f35,0x3f623f80,0xbef10000,0xbe95bf35,0x3f753f35,
0x3dc93f0e,0xbf7fbf55,0x3f223e48,0x3f463f7b,0xbf46bec4,0xbf22bf6d,0x3f7f3f6d,0xbdc93ec4,0xbf75bf7b,0x3e95be48,0x3ef13f55,0xbf62bf0e,
0x3f553f80,0xbf0e0000,0x3f0e0000,0x3f553f80,0xbe483ec4,0xbf7bbf6d,0x3f7b3f6d,0xbe483ec4,0xbf7bbf35,0xbe48bf35,0x3e483f35,0xbf7bbf35,
0xbf0ebf6d,0x3f553ec4,0xbf55bec4,0xbf0ebf6d,0x3f463f80,0xbf220000,0x3f7f3f35,0x3dc93f35,0xbef13e48,0xbf62bf7b,0x3e953f55,0xbf75bf0e,
0xbf75bf6d,0x3e95bec4,0xbf62bec4,0xbef1bf6d,0x3dc9bf0e,0x3f7f3f55,0xbf22bf7b,0x3f463e48,0x3f353f80,0xbf350000,0x3f353f80,0xbf350000,
0xbf350000,0xbf35bf80,0xbf350000,0xbf35bf80,0xbf35bf80,0x3f350000,0xbf35bf80,0x3f350000,0x3f350000,0x3f353f80,0x3f350000,0x3f353f80,
0x3f223f80,0xbf460000,0xbdc93f35,0xbf7fbf35,0xbf62be48,0xbef1bf7b,0xbf75bf55,0x3e95bf0e,0xbe95bf6d,0x3f753ec4,0x3ef1bec4,0x3f623f6d,
0x3f7f3f0e,0x3dc93f55,0x3f463f7b,0xbf223e48,0x3f0e3f80,0xbf550000,0xbf550000,0xbf0ebf80,0xbf7bbec4,0xbe48bf6d,0xbe48bf6d,0x3f7b3ec4,
0x3e48bf35,0x3f7b3f35,0x3f7b3f35,0xbe483f35,0x3f553f6d,0xbf0e3ec4,0xbf0e3ec4,0xbf55bf6d,0x3ef13f80,0xbf620000,0xbf75bf35,0x3e95bf35,
0xbf7fbf0e,0x3dc9bf55,0x3f46be48,0x3f223f7b,0x3f22bec4,0x3f463f6d,0x3dc93f6d,0xbf7fbec4,0x3e953f7b,0xbf75be48,0xbf62bf55,0x3ef1bf0e,
0x3ec43f80,0xbf6d0000,0xbec4bf80,0x3f6d0000,0xbf6dbf35,0x3ec4bf35,0x3f6d3f35,0xbec43f35,0x3f6d0000,0x3ec43f80,0xbf6d0000,0xbec4bf80,
0xbec43f35,0xbf6dbf35,0x3ec4bf35,0x3f6d3f35,0x3e953f80,0xbf750000,0x3ef1bf35,0x3f623f35,0xbf46bf55,0x3f22bf0e,0x3dc93f7b,0xbf7fbe48,
0x3f7f3ec4,0xbdc93f6d,0xbf22bf6d,0x3f46bec4,0xbf623e48,0xbef1bf7b,0x3f753f0e,0xbe953f55,0x3e483f80,0xbf7b0000,0x3f7b0000,0x3e483f80,
0xbf0ebf6d,0x3f55bec4,0xbf553ec4,0xbf0ebf6d,0x3f553f35,0xbf0e3f35,0x3f0ebf35,0x3f553f35,0xbf7bbec4,0x3e48bf6d,0xbe483f6d,0xbf7bbec4,
0x3dc93f80,0xbf7f0000,0x3f463f35,0xbf223f35,0xbe95bf7b,0x3f75be48,0xbf62bf0e,0x3ef1bf55,0x3ef13f6d,0xbf623ec4,0x3f753ec4,0xbe953f6d,
0xbf22bf55,0x3f46bf0e,0xbf7fbe48,0x3dc9bf7b,0x3f80,0xbf800000,0x3f80,0xbf800000,0xbf80,0x3f800000,0xbf80,0x3f800000,
0x3f80,0xbf800000,0x3f80,0xbf800000,0xbf80,0x3f800000,0xbf80,0x3f800000,0xbdc93f80,0xbf7f0000,0xbf463f35,0xbf22bf35,
0x3e95bf7b,0x3f753e48,0x3f62bf0e,0x3ef13f55,0xbef13f6d,0xbf62bec4,0xbf753ec4,0xbe95bf6d,0x3f22bf55,0x3f463f0e,0x3f7fbe48,0x3dc93f7b,
0xbe483f80,0xbf7b0000,0xbf7b0000,0x3e48bf80,0x3f0ebf6d,0x3f553ec4,0x3f553ec4,0xbf0e3f6d,0xbf553f35,0xbf0ebf35,0xbf0ebf35,0x3f55bf35,
0x3f7bbec4,0x3e483f6d,0x3e483f6d,0xbf7b3ec4,0xbe953f80,0xbf750000,0xbef1bf35,0x3f62bf35,0x3f46bf55,0x3f223f0e,0xbdc93f7b,0xbf7f3e48,
0xbf7f3ec4,0xbdc9bf6d,0x3f22bf6d,0x3f463ec4,0x3f623e48,0xbef13f7b,0xbf753f0e,0xbe95bf55,0xbec43f80,0xbf6d0000,0x3ec4bf80,0x3f6d0000,
0x3f6dbf35,0x3ec43f35,0xbf6d3f35,0xbec4bf35,0xbf6d0000,0x3ec4bf80,0x3f6d0000,0xbec43f80,0x3ec43f35,0xbf6d3f35,0xbec4bf35,0x3f6dbf35,
0xbef13f80,0xbf620000,0x3f75bf35,0x3e953f35,0x3f7fbf0e,0x3dc93f55,0xbf46be48,0x3f22bf7b,0xbf22bec4,0x3f46bf6d,0xbdc93f6d,0xbf7f3ec4,
0xbe953f7b,0xbf753e48,0x3f62bf55,0x3ef13f0e,0xbf0e3f80,0xbf550000,0x3f550000,0xbf0e3f80,0x3f7bbec4,0xbe483f6d,0x3e48bf6d,0x3f7bbec4,
0xbe48bf35,0x3f7bbf35,0xbf7b3f35,0xbe48bf35,0xbf553f6d,0xbf0ebec4,0x3f0e3ec4,0xbf553f6d,0xbf223f80,0xbf460000,0x3dc93f35,0xbf7f3f35,
0x3f62be48,0xbef13f7b,0x3f75bf55,0x3e953f0e,0x3e95bf6d,0x3f75bec4,0xbef1bec4,0x3f62bf6d,0xbf7f3f0e,0x3dc9bf55,0xbf463f7b,0xbf22be48,
0xbf353f80,0xbf350000,0xbf353f80,0xbf350000,0x3f350000,0xbf353f80,0x3f350000,0xbf353f80,0x3f35bf80,0x3f350000,0x3f35bf80,0x3f350000,
0xbf350000,0x3f35bf80,0xbf350000,0x3f35bf80,0xbf463f80,0xbf220000,0xbf7f3f35,0x3dc9bf35,0x3ef13e48,0xbf623f7b,0xbe953f55,0xbf753f0e,
0x3f75bf6d,0x3e953ec4,0x3f62bec4,0xbef13f6d,0xbdc9bf0e,0x3f7fbf55,0x3f22bf7b,0x3f46be48,0xbf553f80,0xbf0e0000,0xbf0e0000,0x3f55bf80,
0x3e483ec4,0xbf7b3f6d,0xbf7b3f6d,0xbe48bec4,0x3f7bbf35,0xbe483f35,0xbe483f35,0xbf7b3f35,0x3f0ebf6d,0x3f55bec4,0x3f55bec4,0xbf0e3f6d,
0xbf623f80,0xbef10000,0x3e95bf35,0x3f75bf35,0xbdc93f0e,0xbf7f3f55,0xbf223e48,0x3f46bf7b,0x3f46bec4,0xbf223f6d,0xbf7f3f6d,0xbdc9bec4,
0x3f75bf7b,0x3e953e48,0xbef13f55,0xbf623f0e,0xbf6d3f80,0xbec40000,0x3f6dbf80,0x3ec40000,0xbec43f35,0xbf6d3f35,0x3ec4bf35,0x3f6dbf35,
0x3ec40000,0xbf6d3f80,0xbec40000,0x3f6dbf80,0x3f6dbf35,0xbec43f35,0xbf6d3f35,0x3ec4bf35,0xbf753f80,0xbe950000,0x3f62bf35,0xbef13f35,
0xbf223f55,0xbf463f0e,0x3f7fbf7b,0x3dc93e48,0xbdc93ec4,0xbf7f3f6d,0x3f46bf6d,0x3f22bec4,0x3ef1be48,0xbf623f7b,0x3e95bf0e,0x3f75bf55,
0xbf7b3f80,0xbe480000,0x3e480000,0xbf7b3f80,0xbf553f6d,0xbf0e3ec4,0x3f0ebec4,0xbf553f6d,0xbf0e3f35,0xbf553f35,0x3f55bf35,0xbf0e3f35,
0xbe483ec4,0xbf7b3f6d,0x3f7bbf6d,0xbe483ec4,0xbf7f3f80,0xbdc90000,0xbf223f35,0xbf463f35,0xbf753f7b,0xbe953e48,0xbef13f0e,0xbf623f55,
0xbf623f6d,0xbef13ec4,0xbe953ec4,0xbf753f6d,0xbf463f55,0xbf223f0e,0xbdc93e48,0xbf7f3f7b,0x3f803f80,0xbf803f80,0x3f803f80,0xbf803f80,
0x3f803f80,0xbf803f80,0x3f803f80,0xbf803f80,0x3f803f80,0xbf803f80,0x3f803f80,0xbf803f80,0x3f803f80,0xbf803f80,0x3f803f80,0xbf803f80,
0xbdc90000,0xbf7fbf80,0xbf46bf35,0xbf22bf35,0xbe95be48,0xbf75bf7b,0xbf62bf55,0xbef1bf0e,0xbef1bec4,0xbf62bf6d,0xbf75bf6d,0xbe95bec4,
0xbf22bf0e,0xbf46bf55,0xbf7fbf7b,0xbdc9be48,0xbf7bbf80,0x3e480000,0x3e480000,0x3f7b3f80,0xbf55bf6d,0x3f0e3ec4,0x3f0e3ec4,0x3f553f6d,
0xbf0ebf35,0x3f553f35,0x3f553f35,0x3f0e3f35,0xbe48bec4,0x3f7b3f6d,0x3f7b3f6d,0x3e483ec4,0x3e950000,0x3f753f80,0x3ef13f35,0xbf62bf35,
0x3f463f0e,0x3f223f55,0xbdc93e48,0xbf7fbf7b,0x3f7f3f6d,0x3dc93ec4,0xbf22bec4,0xbf46bf6d,0x3f623f7b,0xbef1be48,0xbf75bf55,0xbe95bf0e,
0x3f6d3f80,0xbec40000,0xbf6dbf80,0x3ec40000,0x3ec43f35,0xbf6dbf35,0xbec4bf35,0x3f6d3f35,0xbec40000,0xbf6dbf80,0x3ec40000,0x3f6d3f80,
0xbf6dbf35,0xbec4bf35,0x3f6d3f35,0x3ec43f35,0xbef10000,0xbf62bf80,0x3f753f35,0x3e953f35,0xbf7fbf55,0xbdc9bf0e,0x3f463f7b,0xbf22be48,
0xbf22bf6d,0x3f463ec4,0xbdc93ec4,0xbf7fbf6d,0x3e95be48,0x3f753f7b,0xbf62bf0e,0xbef1bf55,0xbf55bf80,0x3f0e0000,0xbf0e0000,0xbf55bf80,
0x3e48bec4,0x3f7b3f6d,0xbf7bbf6d,0x3e48bec4,0x3f7b3f35,0x3e483f35,0xbe48bf35,0x3f7b3f35,0x3f0e3f6d,0xbf55bec4,0x3f553ec4,0x3f0e3f6d,
0x3f220000,0x3f463f80,0xbdc9bf35,0x3f7f3f35,0x3f623f7b,0xbef13e48,0x3f753f0e,0x3e953f55,0xbe953ec4,0xbf75bf6d,0x3ef13f6d,0xbf62bec4,
0xbf7fbf55,0x3dc9bf0e,0xbf46be48,0xbf22bf7b,0x3f353f80,0xbf350000,0x3f353f80,0xbf350000,0xbf350000,0xbf35bf80,0xbf350000,0xbf35bf80,
0xbf35bf80,0x3f350000,0xbf35bf80,0x3f350000,0x3f350000,0x3f353f80,0x3f350000,0x3f353f80,0xbf460000,0xbf22bf80,0xbf7fbf35,0x3dc9bf35,
0xbef1bf7b,0x3f623e48,0x3e95bf0e,0x3f753f55,0x3f753ec4,0x3e953f6d,0x3f623f6d,0xbef13ec4,0x3dc93f55,0xbf7fbf0e,0xbf223e48,0xbf46bf7b,
0xbf0ebf80,0x3f550000,0x3f550000,0x3f0e3f80,0x3f7b3ec4,0x3e483f6d,0x3e483f6d,0xbf7bbec4,0xbe483f35,0xbf7bbf35,0xbf7bbf35,0x3e48bf35,
0xbf55bf6d,0x3f0ebec4,0x3f0ebec4,0x3f553f6d,0x3f620000,0x3ef13f80,0xbe953f35,0xbf75bf35,0xbdc93f55,0xbf7fbf0e,0xbf22bf7b,0x3f46be48,
0xbf46bf6d,0x3f22bec4,0x3f7f3ec4,0x3dc93f6d,0x3f753e48,0x3e953f7b,0xbef13f0e,0xbf62bf55,0x3ec43f80,0xbf6d0000,0xbec4bf80,0x3f6d0000,
0xbf6dbf35,0x3ec4bf35,0x3f6d3f35,0xbec43f35,0x3f6d0000,0x3ec43f80,0xbf6d0000,0xbec4bf80,0xbec43f35,0xbf6dbf35,0x3ec4bf35,0x3f6d3f35,
0xbf750000,0xbe95bf80,0x3f623f35,0xbef13f35,0x3f22bf0e,0x3f463f55,0xbf7fbe48,0xbdc9bf7b,0xbdc93f6d,0xbf7fbec4,0x3f46bec4,0x3f223f6d,
0xbef1bf7b,0x3f62be48,0xbe953f55,0xbf75bf0e,0xbe48bf80,0x3f7b0000,0xbf7b0000,0xbe48bf80,0x3f0e3f6d,0xbf553ec4,0x3f55bec4,0x3f0e3f6d,
0xbf55bf35,0x3f0ebf35,0xbf0e3f35,0xbf55bf35,0x3f7b3ec4,0xbe483f6d,0x3e48bf6d,0x3f7b3ec4,0x3f7f0000,0x3dc93f80,0x3f22bf35,0x3f463f35,
0xbf753e48,0xbe95bf7b,0xbef13f55,0xbf62bf0e,0x3f62bec4,0x3ef13f6d,0x3e95bf6d,0x3f753ec4,0xbf463f0e,0xbf22bf55,0xbdc93f7b,0xbf7fbe48,
0x3f80,0xbf800000,0x3f80,0xbf800000,0xbf80,0x3f800000,0xbf80,0x3f800000,0x3f80,0xbf800000,0x3f80,0xbf800000,
0xbf80,0x3f800000,0xbf80,0x3f800000,0xbf7f0000,0x3dc9bf80,0xbf22bf35,0x3f46bf35,0x3f753e48,0xbe953f7b,0x3ef13f55,0xbf623f0e,
0xbf62bec4,0x3ef1bf6d,0xbe95bf6d,0x3f75bec4,0x3f463f0e,0xbf223f55,0x3dc93f7b,0xbf7f3e48,0x3e48bf80,0x3f7b0000,0x3f7b0000,0xbe483f80,
0xbf0e3f6d,0xbf55bec4,0xbf55bec4,0x3f0ebf6d,0x3f55bf35,0x3f0e3f35,0x3f0e3f35,0xbf553f35,0xbf7b3ec4,0xbe48bf6d,0xbe48bf6d,0x3f7bbec4,
0x3f750000,0xbe953f80,0xbf623f35,0xbef1bf35,0xbf22bf0e,0x3f46bf55,0x3f7fbe48,0xbdc93f7b,0x3dc93f6d,0xbf7f3ec4,0xbf46bec4,0x3f22bf6d,
0x3ef1bf7b,0x3f623e48,0x3e953f55,0xbf753f0e,0xbec43f80,0xbf6d0000,0x3ec4bf80,0x3f6d0000,0x3f6dbf35,0x3ec43f35,0xbf6d3f35,0xbec4bf35,
0xbf6d0000,0x3ec4bf80,0x3f6d0000,0xbec43f80,0x3ec43f35,0xbf6d3f35,0xbec4bf35,0x3f6dbf35,0xbf620000,0x3ef1bf80,0x3e953f35,0xbf753f35,
0x3dc93f55,0xbf7f3f0e,0x3f22bf7b,0x3f463e48,0x3f46bf6d,0x3f223ec4,0xbf7f3ec4,0x3dc9bf6d,0xbf753e48,0x3e95bf7b,0x3ef13f0e,0xbf623f55,
0x3f0ebf80,0x3f550000,0xbf550000,0x3f0ebf80,0xbf7b3ec4,0x3e48bf6d,0xbe483f6d,0xbf7b3ec4,0x3e483f35,0xbf7b3f35,0x3f7bbf35,0x3e483f35,
0x3f55bf6d,0x3f0e3ec4,0xbf0ebec4,0x3f55bf6d,0x3f460000,0xbf223f80,0x3f7fbf35,0x3dc93f35,0x3ef1bf7b,0x3f62be48,0xbe95bf0e,0x3f75bf55,
0xbf753ec4,0x3e95bf6d,0xbf623f6d,0xbef1bec4,0xbdc93f55,0xbf7f3f0e,0x3f223e48,0xbf463f7b,0xbf353f80,0xbf350000,0xbf353f80,0xbf350000,
0x3f350000,0xbf353f80,0x3f350000,0xbf353f80,0x3f35bf80,0x3f350000,0x3f35bf80,0x3f350000,0xbf350000,0x3f35bf80,0xbf350000,0x3f35bf80,
0xbf220000,0x3f46bf80,0x3dc9bf35,0x3f7fbf35,0xbf623f7b,0xbef1be48,0xbf753f0e,0x3e95bf55,0x3e953ec4,0xbf753f6d,0xbef13f6d,0xbf623ec4,
0x3f7fbf55,0x3dc93f0e,0x3f46be48,0xbf223f7b,0x3f55bf80,0x3f0e0000,0x3f0e0000,0xbf553f80,0xbe48bec4,0x3f7bbf6d,0x3f7bbf6d,0x3e483ec4,
0xbf7b3f35,0x3e48bf35,0x3e48bf35,0x3f7bbf35,0xbf0e3f6d,0xbf553ec4,0xbf553ec4,0x3f0ebf6d,0x3ef10000,0xbf623f80,0xbf753f35,0x3e95bf35,
0x3f7fbf55,0xbdc93f0e,0xbf463f7b,0xbf223e48,0x3f22bf6d,0x3f46bec4,0x3dc93ec4,0xbf7f3f6d,0xbe95be48,0x3f75bf7b,0x3f62bf0e,0xbef13f55,
0xbf6d3f80,0xbec40000,0x3f6dbf80,0x3ec40000,0xbec43f35,0xbf6d3f35,0x3ec4bf35,0x3f6dbf35,0x3ec40000,0xbf6d3f80,0xbec40000,0x3f6dbf80,
0x3f6dbf35,0xbec43f35,0xbf6d3f35,0x3ec4bf35,0xbe950000,0x3f75bf80,0xbef13f35,0xbf623f35,0xbf463f0e,0x3f22bf55,0x3dc93e48,0xbf7f3f7b,
0xbf7f3f6d,0x3dc9bec4,0x3f22bec4,0xbf463f6d,0xbf623f7b,0xbef13e48,0x3f75bf55,0xbe953f0e,0x3f7bbf80,0x3e480000,0xbe480000,0x3f7bbf80,
0x3f55bf6d,0x3f0ebec4,0xbf0e3ec4,0x3f55bf6d,0x3f0ebf35,0x3f55bf35,0xbf553f35,0x3f0ebf35,0x3e48bec4,0x3f7bbf6d,0xbf7b3f6d,0x3e48bec4,
0x3dc90000,0xbf7f3f80,0x3f46bf35,0xbf223f35,0x3e95be48,0xbf753f7b,0x3f62bf55,0xbef13f0e,0x3ef1bec4,0xbf623f6d,0x3f75bf6d,0xbe953ec4,
0x3f22bf0e,0xbf463f55,0x3f7fbf7b,0xbdc93e48,0x3f803f80,0xbf803f80,0x3f803f80,0xbf803f80,0x3f803f80,0xbf803f80,0x3f803f80,0xbf803f80,
0x3f803f80,0xbf803f80,0x3f803f80,0xbf803f80,0x3f803f80,0xbf803f80,0x3f803f80,0xbf803f80,0xbf7fbf80,0x3dc90000,0xbf22bf35,0x3f463f35,
0xbf75bf7b,0x3e953e48,0xbef1bf0e,0x3f623f55,0xbf62bf6d,0x3ef13ec4,0xbe95bec4,0x3f753f6d,0xbf46bf55,0x3f223f0e,0xbdc9be48,0x3f7f3f7b,
0x3f7b3f80,0xbe480000,0xbe480000,0xbf7bbf80,0x3f553f6d,0xbf0ebec4,0xbf0ebec4,0xbf55bf6d,0x3f0e3f35,0xbf55bf35,0xbf55bf35,0xbf0ebf35,
0x3e483ec4,0xbf7bbf6d,0xbf7bbf6d,0xbe48bec4,0xbf75bf80,0x3e950000,0x3f623f35,0x3ef13f35,0xbf22bf55,0x3f463f0e,0x3f7f3f7b,0xbdc93e48,
0xbdc9bec4,0x3f7f3f6d,0x3f463f6d,0xbf22bec4,0x3ef13e48,0x3f623f7b,0x3e953f0e,0xbf75bf55,0x3f6d3f80,0xbec40000,0xbf6dbf80,0x3ec40000,
0x3ec43f35,0xbf6dbf35,0xbec4bf35,0x3f6d3f35,0xbec40000,0xbf6dbf80,0x3ec40000,0x3f6d3f80,0xbf6dbf35,0xbec4bf35,0x3f6d3f35,0x3ec43f35,
0xbf62bf80,0x3ef10000,0x3e953f35,0xbf75bf35,0xbdc9bf0e,0x3f7f3f55,0xbf22be48,0xbf46bf7b,0x3f463ec4,0x3f223f6d,0xbf7fbf6d,0x3dc9bec4,
0x3f753f7b,0xbe953e48,0xbef1bf55,0x3f623f0e,0x3f553f80,0xbf0e0000,0x3f0e0000,0x3f553f80,0xbe483ec4,0xbf7bbf6d,0x3f7b3f6d,0xbe483ec4,
0xbf7bbf35,0xbe48bf35,0x3e483f35,0xbf7bbf35,0xbf0ebf6d,0x3f553ec4,0xbf55bec4,0xbf0ebf6d,0xbf46bf80,0x3f220000,0xbf7fbf35,0xbdc9bf35,
0x3ef1be48,0x3f623f7b,0xbe95bf55,0x3f753f0e,0x3f753f6d,0xbe953ec4,0x3f623ec4,0x3ef13f6d,0xbdc93f0e,0xbf7fbf55,0x3f223f7b,0xbf46be48,
0x3f353f80,0xbf350000,0x3f353f80,0xbf350000,0xbf350000,0xbf35bf80,0xbf350000,0xbf35bf80,0xbf35bf80,0x3f350000,0xbf35bf80,0x3f350000,
0x3f350000,0x3f353f80,0x3f350000,0x3f353f80,0xbf22bf80,0x3f460000,0x3dc9bf35,0x3f7f3f35,0x3f623e48,0x3ef13f7b,0x3f753f55,0xbe953f0e,
0x3e953f6d,0xbf75bec4,0xbef13ec4,0xbf62bf6d,0xbf7fbf0e,0xbdc9bf55,0xbf46bf7b,0x3f22be48,0x3f0e3f80,0xbf550000,0xbf550000,0xbf0ebf80,
0xbf7bbec4,0xbe48bf6d,0xbe48bf6d,0x3f7b3ec4,0x3e48bf35,0x3f7b3f35,0x3f7b3f35,0xbe483f35,0x3f553f6d,0xbf0e3ec4,0xbf0e3ec4,0xbf55bf6d,
0xbef1bf80,0x3f620000,0x3f753f35,0xbe953f35,0x3f7f3f0e,0xbdc93f55,0xbf463e48,0xbf22bf7b,0xbf223ec4,0xbf46bf6d,0xbdc9bf6d,0x3f7f3ec4,
0xbe95bf7b,0x3f753e48,0x3f623f55,0xbef13f0e,0x3ec43f80,0xbf6d0000,0xbec4bf80,0x3f6d0000,0xbf6dbf35,0x3ec4bf35,0x3f6d3f35,0xbec43f35,
0x3f6d0000,0x3ec43f80,0xbf6d0000,0xbec4bf80,0xbec43f35,0xbf6dbf35,0x3ec4bf35,0x3f6d3f35,0xbe95bf80,0x3f750000,0xbef13f35,0xbf62bf35,
0x3f463f55,0xbf223f0e,0xbdc9bf7b,0x3f7f3e48,0xbf7fbec4,0x3dc9bf6d,0x3f223f6d,0xbf463ec4,0x3f62be48,0x3ef13f7b,0xbf75bf0e,0x3e95bf55,
0x3e483f80,0xbf7b0000,0x3f7b0000,0x3e483f80,0xbf0ebf6d,0x3f55bec4,0xbf553ec4,0xbf0ebf6d,0x3f553f35,0xbf0e3f35,0x3f0ebf35,0x3f553f35,
0xbf7bbec4,0x3e48bf6d,0xbe483f6d,0xbf7bbec4,0xbdc9bf80,0x3f7f0000,0xbf46bf35,0x3f22bf35,0x3e953f7b,0xbf753e48,0x3f623f0e,0xbef13f55,
0xbef1bf6d,0x3f62bec4,0xbf75bec4,0x3e95bf6d,0x3f223f55,0xbf463f0e,0x3f7f3e48,0xbdc93f7b,0x3f80,0xbf800000,0x3f80,0xbf800000,
0xbf80,0x3f800000,0xbf80,0x3f800000,0x3f80,0xbf800000,0x3f80,0xbf800000,0xbf80,0x3f800000,0xbf80,0x3f800000,
0x3dc9bf80,0x3f7f0000,0x3f46bf35,0x3f223f35,0xbe953f7b,0xbf75be48,0xbf623f0e,0xbef1bf55,0x3ef1bf6d,0x3f623ec4,0x3f75bec4,0x3e953f6d,
0xbf223f55,0xbf46bf0e,0xbf7f3e48,0xbdc9bf7b,0xbe483f80,0xbf7b0000,0xbf7b0000,0x3e48bf80,0x3f0ebf6d,0x3f553ec4,0x3f553ec4,0xbf0e3f6d,
0xbf553f35,0xbf0ebf35,0xbf0ebf35,0x3f55bf35,0x3f7bbec4,0x3e483f6d,0x3e483f6d,0xbf7b3ec4,0x3e95bf80,0x3f750000,0x3ef13f35,0xbf623f35,
0xbf463f55,0xbf22bf0e,0x3dc9bf7b,0x3f7fbe48,0x3f7fbec4,0x3dc93f6d,0xbf223f6d,0xbf46bec4,0xbf62be48,0x3ef1bf7b,0x3f75bf0e,0x3e953f55,
0xbec43f80,0xbf6d0000,0x3ec4bf80,0x3f6d0000,0x3f6dbf35,0x3ec43f35,0xbf6d3f35,0xbec4bf35,0xbf6d0000,0x3ec4bf80,0x3f6d0000,0xbec43f80,
0x3ec43f35,0xbf6d3f35,0xbec4bf35,0x3f6dbf35,0x3ef1bf80,0x3f620000,0xbf753f35,0xbe95bf35,0xbf7f3f0e,0xbdc9bf55,0x3f463e48,0xbf223f7b,
0x3f223ec4,0xbf463f6d,0x3dc9bf6d,0x3f7fbec4,0x3e95bf7b,0x3f75be48,0xbf623f55,0xbef1bf0e,0xbf0e3f80,0xbf550000,0x3f550000,0xbf0e3f80,
0x3f7bbec4,0xbe483f6d,0x3e48bf6d,0x3f7bbec4,0xbe48bf35,0x3f7bbf35,0xbf7b3f35,0xbe48bf35,0xbf553f6d,0xbf0ebec4,0x3f0e3ec4,0xbf553f6d,
0x3f22bf80,0x3f460000,0xbdc9bf35,0x3f7fbf35,0xbf623e48,0x3ef1bf7b,0xbf753f55,0xbe95bf0e,0xbe953f6d,0xbf753ec4,0x3ef13ec4,0xbf623f6d,
0x3f7fbf0e,0xbdc93f55,0x3f46bf7b,0x3f223e48,0xbf353f80,0xbf350000,0xbf353f80,0xbf350000,0x3f350000,0xbf353f80,0x3f350000,0xbf353f80,
0x3f35bf80,0x3f350000,0x3f35bf80,0x3f350000,0xbf350000,0x3f35bf80,0xbf350000,0x3f35bf80,0x3f46bf80,0x3f220000,0x3f7fbf35,0xbdc93f35,
0xbef1be48,0x3f62bf7b,0x3e95bf55,0x3f75bf0e,0xbf753f6d,0xbe95bec4,0xbf623ec4,0x3ef1bf6d,0x3dc93f0e,0xbf7f3f55,0xbf223f7b,0xbf463e48,
0xbf553f80,0xbf0e0000,0xbf0e0000,0x3f55bf80,0x3e483ec4,0xbf7b3f6d,0xbf7b3f6d,0xbe48bec4,0x3f7bbf35,0xbe483f35,0xbe483f35,0xbf7b3f35,
0x3f0ebf6d,0x3f55bec4,0x3f55bec4,0xbf0e3f6d,0x3f62bf80,0x3ef10000,0xbe953f35,0xbf753f35,0x3dc9bf0e,0x3f7fbf55,0x3f22be48,0xbf463f7b,
0xbf463ec4,0x3f22bf6d,0x3f7fbf6d,0x3dc93ec4,0xbf753f7b,0xbe95be48,0x3ef1bf55,0x3f62bf0e,0xbf6d3f80,0xbec40000,0x3f6dbf80,0x3ec40000,
0xbec43f35,0xbf6d3f35,0x3ec4bf35,0x3f6dbf35,0x3ec40000,0xbf6d3f80,0xbec40000,0x3f6dbf80,0x3f6dbf35,0xbec43f35,0xbf6d3f35,0x3ec4bf35,
0x3f75bf80,0x3e950000,0xbf623f35,0x3ef1bf35,0x3f22bf55,0x3f46bf0e,0xbf7f3f7b,0xbdc9be48,0x3dc9bec4,0x3f7fbf6d,0xbf463f6d,0xbf223ec4,
0xbef13e48,0x3f62bf7b,0xbe953f0e,0xbf753f55,0xbf7b3f80,0xbe480000,0x3e480000,0xbf7b3f80,0xbf553f6d,0xbf0e3ec4,0x3f0ebec4,0xbf553f6d,
0xbf0e3f35,0xbf553f35,0x3f55bf35,0xbf0e3f35,0xbe483ec4,0xbf7b3f6d,0x3f7bbf6d,0xbe483ec4,0x3f7fbf80,0x3dc90000,0x3f22bf35,0x3f46bf35,
0x3f75bf7b,0x3e95be48,0x3ef1bf0e,0x3f62bf55,0x3f62bf6d,0x3ef1bec4,0x3e95bec4,0x3f75bf6d,0x3f46bf55,0x3f22bf0e,0x3dc9be48,0x3f7fbf7b,
0x3f803f80,0xbf803f80,0x3f803f80,0xbf803f80,0x3f803f80,0xbf803f80,0x3f803f80,0xbf803f80,0x3f803f80,0xbf803f80,0x3f803f80,0xbf803f80,
0x3f803f80,0xbf803f80,0x3f803f80,0xbf803f80,0x3dc90000,0x3f7f3f80,0x3f463f35,0x3f223f35,0x3e953e48,0x3f753f7b,0x3f623f55,0x3ef13f0e,
0x3ef13ec4,0x3f623f6d,0x3f753f6d,0x3e953ec4,0x3f223f0e,0x3f463f55,0x3f7f3f7b,0x3dc93e48,0xbf7bbf80,0x3e480000,0x3e480000,0x3f7b3f80,
0xbf55bf6d,0x3f0e3ec4,0x3f0e3ec4,0x3f553f6d,0xbf0ebf35,0x3f553f35,0x3f553f35,0x3f0e3f35,0xbe48bec4,0x3f7b3f6d,0x3f7b3f6d,0x3e483ec4,
0xbe950000,0xbf75bf80,0xbef1bf35,0x3f623f35,0xbf46bf0e,0xbf22bf55,0x3dc9be48,0x3f7f3f7b,0xbf7fbf6d,0xbdc9bec4,0x3f223ec4,0x3f463f6d,
0xbf62bf7b,0x3ef13e48,0x3f753f55,0x3e953f0e,0x3f6d3f80,0xbec40000,0xbf6dbf80,0x3ec40000,0x3ec43f35,0xbf6dbf35,0xbec4bf35,0x3f6d3f35,
0xbec40000,0xbf6dbf80,0x3ec40000,0x3f6d3f80,0xbf6dbf35,0xbec4bf35,0x3f6d3f35,0x3ec43f35,0x3ef10000,0x3f623f80,0xbf75bf35,0xbe95bf35,
0x3f7f3f55,0x3dc93f0e,0xbf46bf7b,0x3f223e48,0x3f223f6d,0xbf46bec4,0x3dc9bec4,0x3f7f3f6d,0xbe953e48,0xbf75bf7b,0x3f623f0e,0x3ef13f55,
0xbf55bf80,0x3f0e0000,0xbf0e0000,0xbf55bf80,0x3e48bec4,0x3f7b3f6d,0xbf7bbf6d,0x3e48bec4,0x3f7b3f35,0x3e483f35,0xbe48bf35,0x3f7b3f35,
0x3f0e3f6d,0xbf55bec4,0x3f553ec4,0x3f0e3f6d,0xbf220000,0xbf46bf80,0x3dc93f35,0xbf7fbf35,0xbf62bf7b,0x3ef1be48,0xbf75bf0e,0xbe95bf55,
0x3e95bec4,0x3f753f6d,0xbef1bf6d,0x3f623ec4,0x3f7f3f55,0xbdc93f0e,0x3f463e48,0x3f223f7b,0x3f353f80,0xbf350000,0x3f353f80,0xbf350000,
0xbf350000,0xbf35bf80,0xbf350000,0xbf35bf80,0xbf35bf80,0x3f350000,0xbf35bf80,0x3f350000,0x3f350000,0x3f353f80,0x3f350000,0x3f353f80,
0x3f460000,0x3f223f80,0x3f7f3f35,0xbdc93f35,0x3ef13f7b,0xbf62be48,0xbe953f0e,0xbf75bf55,0xbf75bec4,0xbe95bf6d,0xbf62bf6d,0x3ef1bec4,
0xbdc9bf55,0x3f7f3f0e,0x3f22be48,0x3f463f7b,0xbf0ebf80,0x3f550000,0x3f550000,0x3f0e3f80,0x3f7b3ec4,0x3e483f6d,0x3e483f6d,0xbf7bbec4,
0xbe483f35,0xbf7bbf35,0xbf7bbf35,0x3e48bf35,0xbf55bf6d,0x3f0ebec4,0x3f0ebec4,0x3f553f6d,0xbf620000,0xbef1bf80,0x3e95bf35,0x3f753f35,
0x3dc9bf55,0x3f7f3f0e,0x3f223f7b,0xbf463e48,0x3f463f6d,0xbf223ec4,0xbf7fbec4,0xbdc9bf6d,0xbf75be48,0xbe95bf7b,0x3ef1bf0e,0x3f623f55,
0x3ec43f80,0xbf6d0000,0xbec4bf80,0x3f6d0000,0xbf6dbf35,0x3ec4bf35,0x3f6d3f35,0xbec43f35,0x3f6d0000,0x3ec43f80,0xbf6d0000,0xbec4bf80,
0xbec43f35,0xbf6dbf35,0x3ec4bf35,0x3f6d3f35,0x3f750000,0x3e953f80,0xbf62bf35,0x3ef1bf35,0xbf223f0e,0xbf46bf55,0x3f7f3e48,0x3dc93f7b,
0x3dc9bf6d,0x3f7f3ec4,0xbf463ec4,0xbf22bf6d,0x3ef13f7b,0xbf623e48,0x3e95bf55,0x3f753f0e,0xbe48bf80,0x3f7b0000,0xbf7b0000,0xbe48bf80,
0x3f0e3f6d,0xbf553ec4,0x3f55bec4,0x3f0e3f6d,0xbf55bf35,0x3f0ebf35,0xbf0e3f35,0xbf55bf35,0x3f7b3ec4,0xbe483f6d,0x3e48bf6d,0x3f7b3ec4,
0xbf7f0000,0xbdc9bf80,0xbf223f35,0xbf46bf35,0x3f75be48,0x3e953f7b,0x3ef1bf55,0x3f623f0e,0xbf623ec4,0xbef1bf6d,0xbe953f6d,0xbf75bec4,
0x3f46bf0e,0x3f223f55,0x3dc9bf7b,0x3f7f3e48,0x3f80,0xbf800000,0x3f80,0xbf800000,0xbf80,0x3f800000,0xbf80,0x3f800000,
0x3f80,0xbf800000,0x3f80,0xbf800000,0xbf80,0x3f800000,0xbf80,0x3f800000,0x3f7f0000,0xbdc93f80,0x3f223f35,0xbf463f35,
0xbf75be48,0x3e95bf7b,0xbef1bf55,0x3f62bf0e,0x3f623ec4,0xbef13f6d,0x3e953f6d,0xbf753ec4,0xbf46bf0e,0x3f22bf55,0xbdc9bf7b,0x3f7fbe48,
0x3e48bf80,0x3f7b0000,0x3f7b0000,0xbe483f80,0xbf0e3f6d,0xbf55bec4,0xbf55bec4,0x3f0ebf6d,0x3f55bf35,0x3f0e3f35,0x3f0e3f35,0xbf553f35,
0xbf7b3ec4,0xbe48bf6d,0xbe48bf6d,0x3f7bbec4,0xbf750000,0x3e95bf80,0x3f62bf35,0x3ef13f35,0x3f223f0e,0xbf463f55,0xbf7f3e48,0x3dc9bf7b,
0xbdc9bf6d,0x3f7fbec4,0x3f463ec4,0xbf223f6d,0xbef13f7b,0xbf62be48,0xbe95bf55,0x3f75bf0e,0xbec43f80,0xbf6d0000,0x3ec4bf80,0x3f6d0000,
0x3f6dbf35,0x3ec43f35,0xbf6d3f35,0xbec4bf35,0xbf6d0000,0x3ec4bf80,0x3f6d0000,0xbec43f80,0x3ec43f35,0xbf6d3f35,0xbec4bf35,0x3f6dbf35,
0x3f620000,0xbef13f80,0xbe95bf35,0x3f75bf35,0xbdc9bf55,0x3f7fbf0e,0xbf223f7b,0xbf46be48,0xbf463f6d,0xbf22bec4,0x3f7fbec4,0xbdc93f6d,
0x3f75be48,0xbe953f7b,0xbef1bf0e,0x3f62bf55,0x3f0ebf80,0x3f550000,0xbf550000,0x3f0ebf80,0xbf7b3ec4,0x3e48bf6d,0xbe483f6d,0xbf7b3ec4,
0x3e483f35,0xbf7b3f35,0x3f7bbf35,0x3e483f35,0x3f55bf6d,0x3f0e3ec4,0xbf0ebec4,0x3f55bf6d,0xbf460000,0x3f22bf80,0xbf7f3f35,0xbdc9bf35,
0xbef13f7b,0xbf623e48,0x3e953f0e,0xbf753f55,0x3f75bec4,0xbe953f6d,0x3f62bf6d,0x3ef13ec4,0x3dc9bf55,0x3f7fbf0e,0xbf22be48,0x3f46bf7b,
0xbf353f80,0xbf350000,0xbf353f80,0xbf350000,0x3f350000,0xbf353f80,0x3f350000,0xbf353f80,0x3f35bf80,0x3f350000,0x3f35bf80,0x3f350000,
0xbf350000,0x3f35bf80,0xbf350000,0x3f35bf80,0x3f220000,0xbf463f80,0xbdc93f35,0xbf7f3f35,0x3f62bf7b,0x3ef13e48,0x3f75bf0e,0xbe953f55,
0xbe95bec4,0x3f75bf6d,0x3ef1bf6d,0x3f62bec4,0xbf7f3f55,0xbdc9bf0e,0xbf463e48,0x3f22bf7b,0x3f55bf80,0x3f0e0000,0x3f0e0000,0xbf553f80,
0xbe48bec4,0x3f7bbf6d,0x3f7bbf6d,0x3e483ec4,0xbf7b3f35,0x3e48bf35,0x3e48bf35,0x3f7bbf35,0xbf0e3f6d,0xbf553ec4,0xbf553ec4,0x3f0ebf6d,
0xbef10000,0x3f62bf80,0x3f75bf35,0xbe953f35,0xbf7f3f55,0x3dc9bf0e,0x3f46bf7b,0x3f22be48,0xbf223f6d,0xbf463ec4,0xbdc9bec4,0x3f7fbf6d,
0x3e953e48,0xbf753f7b,0xbf623f0e,0x3ef1bf55,0xbf6d3f80,0xbec40000,0x3f6dbf80,0x3ec40000,0xbec43f35,0xbf6d3f35,0x3ec4bf35,0x3f6dbf35,
0x3ec40000,0xbf6d3f80,0xbec40000,0x3f6dbf80,0x3f6dbf35,0xbec43f35,0xbf6d3f35,0x3ec4bf35,0x3e950000,0xbf753f80,0x3ef1bf35,0x3f62bf35,
0x3f46bf0e,0xbf223f55,0xbdc9be48,0x3f7fbf7b,0x3f7fbf6d,0xbdc93ec4,0xbf223ec4,0x3f46bf6d,0x3f62bf7b,0x3ef1be48,0xbf753f55,0x3e95bf0e,
0x3f7bbf80,0x3e480000,0xbe480000,0x3f7bbf80,0x3f55bf6d,0x3f0ebec4,0xbf0e3ec4,0x3f55bf6d,0x3f0ebf35,0x3f55bf35,0xbf553f35,0x3f0ebf35,
0x3e48bec4,0x3f7bbf6d,0xbf7b3f6d,0x3e48bec4,0xbdc90000,0x3f7fbf80,0xbf463f35,0x3f22bf35,0xbe953e48,0x3f75bf7b,0xbf623f55,0x3ef1bf0e,
0xbef13ec4,0x3f62bf6d,0xbf753f6d,0x3e95bec4,0xbf223f0e,0x3f46bf55,0xbf7f3f7b,0x3dc9be48,0x40003f80,0x3fb53f80,0x3f80,0xbfb53f80,
0x40004000,0xbfb50000,0x0,0xbfb5c000,0x40004000,0xbfb5c000,0x0,0x3fb50000,0x40004000,0x3fb50000,0x0,0x3fb54000,
0x3fff3f80,0x3fa23f80,0xbe49bf80,0xbfc6bf80,0x3ff53ffb,0xbfe2bec8,0xbf15bec8,0xbf71bffb,0x3fe23fed,0xbf15bfed,0xbf71bf44,0x3ff53f44,
0x3fc63fd5,0x3fff3f8e,0xbfa2bf8e,0x3e493fd5,0x3ffb3f80,0x3f8e3f80,0xbec83f80,0xbfd53f80,0x3fd53fed,0xbffbbf44,0xbf8ebf44,0xbec8bfed,
0x3f8e3fb5,0x3ec8bfb5,0xbfd5bfb5,0x3ffb3fb5,0x3ec83f44,0x3fd53fed,0xbffbbfed,0xbf8e3f44,0x3ff53f80,0x3f713f80,0xbf15bf80,0xbfe2bf80,
0x3fa23fd5,0xbfffbf8e,0xbfc6bf8e,0x3e49bfd5,0x3e493f44,0x3fa2bf44,0xbfffbfed,0x3fc63fed,0xbf71bec8,0x3f153ffb,0xbfe2bffb,0xbff5bec8,
0x3fed3f80,0x3f443f80,0xbf443f80,0xbfed3f80,0x3f443fb5,0xbfedbfb5,0xbfedbfb5,0x3f44bfb5,0xbf440000,0x3fed0000,0xbfedc000,0x3f444000,
0xbfedbfb5,0xbf443fb5,0xbf44bfb5,0xbfedbfb5,0x3fe23f80,0x3f153f80,0xbf71bf80,0xbff5bf80,0x3e493f8e,0xbfc6bfd5,0xbfffbfd5,0x3fa2bf8e,
0xbfc6bf44,0x3fff3f44,0xbfa2bfed,0xbe493fed,0xbff5bffb,0xbfe23ec8,0x3f15bec8,0xbf71bffb,0x3fd53f80,0x3ec83f80,0xbf8e3f80,0xbffb3f80,
0xbec83f44,0xbf8ebfed,0xbffbbfed,0x3fd5bf44,0xbffbbfb5,0x3fd53fb5,0xbec8bfb5,0xbf8e3fb5,0xbf8ebfed,0xbffbbf44,0x3fd53f44,0x3ec8bfed,
0x3fc63f80,0x3e493f80,0xbfa2bf80,0xbfffbf80,0xbf713ec8,0xbf15bffb,0xbfe2bffb,0x3ff5bec8,0xbff5bfed,0x3f713fed,0x3f15bf44,0xbfe23f44,
0x3e49bf8e,0xbfa2bfd5,0x3fff3fd5,0x3fc6bf8e,0x3f80,0xbfb53f80,0xc0003f80,0xbfb53f80,0xc000,0x3fb50000,0x40000000,0xbfb54000,
0x4000,0x3fb5c000,0xc0000000,0x3fb50000,0xc000,0xbfb50000,0x40000000,0x3fb5c000,0xbe493f80,0xbfc63f80,0xbfffbf80,0xbfa2bf80,
0x3f15bffb,0x3f713ec8,0x3ff53ec8,0xbfe23ffb,0xbf713fed,0x3ff5bfed,0xbfe2bf44,0x3f153f44,0x3fa2bfd5,0xbe49bf8e,0x3fc63f8e,0x3fffbfd5,
0xbec83f80,0xbfd53f80,0xbffb3f80,0xbf8e3f80,0x3f8ebfed,0x3ec83f44,0x3fd53f44,0xbffb3fed,0xbfd53fb5,0x3ffbbfb5,0xbf8ebfb5,0xbec83fb5,
0x3ffbbf44,0x3f8ebfed,0x3ec83fed,0x3fd5bf44,0xbf153f80,0xbfe23f80,0xbff5bf80,0xbf71bf80,0x3fc6bfd5,0xbe493f8e,0x3fa23f8e,0xbfff3fd5,
0xbfff3f44,0x3fc6bf44,0xbe49bfed,0xbfa23fed,0x3fe23ec8,0x3ff5bffb,0xbf713ffb,0x3f153ec8,0xbf443f80,0xbfed3f80,0xbfed3f80,0xbf443f80,
0x3fedbfb5,0xbf443fb5,0x3f443fb5,0xbfed3fb5,0xbfed0000,0x3f440000,0x3f44c000,0xbfed4000,0x3f443fb5,0x3fedbfb5,0xbfed3fb5,0xbf443fb5,
0xbf713f80,0xbff53f80,0xbfe2bf80,0xbf15bf80,0x3fffbf8e,0xbfa23fd5,0x3e493fd5,0xbfc63f8e,0xbfa2bf44,0xbe493f44,0x3fc6bfed,0xbfff3fed,
0xbf153ffb,0x3f71bec8,0xbff53ec8,0xbfe23ffb,0xbf8e3f80,0xbffb3f80,0xbfd53f80,0xbec83f80,0x3ffbbf44,0xbfd53fed,0xbec83fed,0xbf8e3f44,
0xbec8bfb5,0xbf8e3fb5,0x3ffbbfb5,0xbfd53fb5,0xbfd53fed,0xbec83f44,0xbf8ebf44,0xbffb3fed,0xbfa23f80,0xbfff3f80,0xbfc6bf80,0xbe49bf80,
0x3fe2bec8,0xbff53ffb,0xbf713ffb,0xbf153ec8,0x3f15bfed,0xbfe23fed,0x3ff5bf44,0xbf713f44,0xbfff3f8e,0xbfc63fd5,0x3e49bfd5,0xbfa23f8e,
0xc0003f80,0xbfb53f80,0x3f80,0x3fb53f80,0xc0004000,0x3fb50000,0x0,0x3fb5c000,0xc0004000,0x3fb5c000,0x0,0xbfb50000,
0xc0004000,0xbfb50000,0x0,0xbfb54000,0xbfff3f80,0xbfa23f80,0x3e49bf80,0x3fc6bf80,0xbff53ffb,0x3fe2bec8,0x3f15bec8,0x3f71bffb,
0xbfe23fed,0x3f15bfed,0x3f71bf44,0xbff53f44,0xbfc63fd5,0xbfff3f8e,0x3fa2bf8e,0xbe493fd5,0xbffb3f80,0xbf8e3f80,0x3ec83f80,0x3fd53f80,
0xbfd53fed,0x3ffbbf44,0x3f8ebf44,0x3ec8bfed,0xbf8e3fb5,0xbec8bfb5,0x3fd5bfb5,0xbffb3fb5,0xbec83f44,0xbfd53fed,0x3ffbbfed,0x3f8e3f44,
0xbff53f80,0xbf713f80,0x3f15bf80,0x3fe2bf80,0xbfa23fd5,0x3fffbf8e,0x3fc6bf8e,0xbe49bfd5,0xbe493f44,0xbfa2bf44,0x3fffbfed,0xbfc63fed,
0x3f71bec8,0xbf153ffb,0x3fe2bffb,0x3ff5bec8,0xbfed3f80,0xbf443f80,0x3f443f80,0x3fed3f80,0xbf443fb5,0x3fedbfb5,0x3fedbfb5,0xbf44bfb5,
0x3f440000,0xbfed0000,0x3fedc000,0xbf444000,0x3fedbfb5,0x3f443fb5,0x3f44bfb5,0x3fedbfb5,0xbfe23f80,0xbf153f80,0x3f71bf80,0x3ff5bf80,
0xbe493f8e,0x3fc6bfd5,0x3fffbfd5,0xbfa2bf8e,0x3fc6bf44,0xbfff3f44,0x3fa2bfed,0x3e493fed,0x3ff5bffb,0x3fe23ec8,0xbf15bec8,0x3f71bffb,
0xbfd53f80,0xbec83f80,0x3f8e3f80,0x3ffb3f80,0x3ec83f44,0x3f8ebfed,0x3ffbbfed,0xbfd5bf44,0x3ffbbfb5,0xbfd53fb5,0x3ec8bfb5,0x3f8e3fb5,
0x3f8ebfed,0x3ffbbf44,0xbfd53f44,0xbec8bfed,0xbfc63f80,0xbe493f80,0x3fa2bf80,0x3fffbf80,0x3f713ec8,0x3f15bffb,0x3fe2bffb,0xbff5bec8,
0x3ff5bfed,0xbf713fed,0xbf15bf44,0x3fe23f44,0xbe49bf8e,0x3fa2bfd5,0xbfff3fd5,0xbfc6bf8e,0x3f80,0x3fb53f80,0x40003f80,0x3fb53f80,
0xc000,0xbfb50000,0xc0000000,0x3fb54000,0x4000,0xbfb5c000,0x40000000,0xbfb50000,0xc000,0x3fb50000,0xc0000000,0xbfb5c000,
0x3e493f80,0x3fc63f80,0x3fffbf80,0x3fa2bf80,0xbf15bffb,0xbf713ec8,0xbff53ec8,0x3fe23ffb,0x3f713fed,0xbff5bfed,0x3fe2bf44,0xbf153f44,
0xbfa2bfd5,0x3e49bf8e,0xbfc63f8e,0xbfffbfd5,0x3ec83f80,0x3fd53f80,0x3ffb3f80,0x3f8e3f80,0xbf8ebfed,0xbec83f44,0xbfd53f44,0x3ffb3fed,
0x3fd53fb5,0xbffbbfb5,0x3f8ebfb5,0x3ec83fb5,0xbffbbf44,0xbf8ebfed,0xbec83fed,0xbfd5bf44,0x3f153f80,0x3fe23f80,0x3ff5bf80,0x3f71bf80,
0xbfc6bfd5,0x3e493f8e,0xbfa23f8e,0x3fff3fd5,0x3fff3f44,0xbfc6bf44,0x3e49bfed,0x3fa23fed,0xbfe23ec8,0xbff5bffb,0x3f713ffb,0xbf153ec8,
0x3f443f80,0x3fed3f80,0x3fed3f80,0x3f443f80,0xbfedbfb5,0x3f443fb5,0xbf443fb5,0x3fed3fb5,0x3fed0000,0xbf440000,0xbf44c000,0x3fed4000,
0xbf443fb5,0xbfedbfb5,0x3fed3fb5,0x3f443fb5,0x3f713f80,0x3ff53f80,0x3fe2bf80,0x3f15bf80,0xbfffbf8e,0x3fa23fd5,0xbe493fd5,0x3fc63f8e,
0x3fa2bf44,0x3e493f44,0xbfc6bfed,0x3fff3fed,0x3f153ffb,0xbf71bec8,0x3ff53ec8,0x3fe23ffb,0x3f8e3f80,0x3ffb3f80,0x3fd53f80,0x3ec83f80,
0xbffbbf44,0x3fd53fed,0x3ec83fed,0x3f8e3f44,0x3ec8bfb5,0x3f8e3fb5,0xbffbbfb5,0x3fd53fb5,0x3fd53fed,0x3ec83f44,0x3f8ebf44,0x3ffb3fed,
0x3fa23f80,0x3fff3f80,0x3fc6bf80,0x3e49bf80,0xbfe2bec8,0x3ff53ffb,0x3f713ffb,0x3f153ec8,0xbf15bfed,0x3fe23fed,0xbff5bf44,0x3f713f44,
0x3fff3f8e,0x3fc63fd5,0xbe49bfd5,0x3fa23f8e,0x40004000,0x3fb54000,0x0,0xbfb50000,0x40004000,0xbfb50000,0x0,0xbfb5c000,
0x40004000,0xbfb5c000,0x0,0x3fb50000,0x40004000,0x3fb50000,0x0,0x3fb54000,0x3fa23fb5,0xbe493fb5,0xbfc6bfb5,0xbfffbfb5,
0x3f713f8e,0xbff5bfd5,0xbfe2bfd5,0x3f15bf8e,0x3f153f44,0x3f71bf44,0xbff5bfed,0x3fe23fed,0x3e493ec8,0x3fc63ffb,0xbfffbffb,0xbfa23ec8,
0xbec80000,0xbfd50000,0xbffbc000,0xbf8ec000,0xbf8ebf44,0xbec8bfed,0xbfd5bfed,0x3ffb3f44,0xbfd5bfb5,0x3ffb3fb5,0xbf8ebfb5,0xbec83fb5,
0xbffbbfed,0xbf8e3f44,0xbec8bf44,0xbfd5bfed,0xbfe2bfb5,0xbff5bfb5,0xbf71bfb5,0x3f15bfb5,0xbfffbffb,0x3fc6bec8,0x3e49bec8,0x3fa23ffb,
0xbfc6bfed,0x3e493fed,0x3fa23f44,0xbfffbf44,0xbf15bf8e,0xbfe2bfd5,0x3ff53fd5,0x3f71bf8e,0xbfedc000,0xbf44c000,0x3f440000,0x3fed0000,
0xbf44bfb5,0x3fed3fb5,0x3fed3fb5,0xbf443fb5,0x3f440000,0xbfed0000,0x3fed4000,0xbf44c000,0x3fed3fb5,0x3f44bfb5,0x3f443fb5,0x3fed3fb5,
0xbf15bfb5,0x3f71bfb5,0x3ff53fb5,0x3fe23fb5,0x3fa23ec8,0x3e493ffb,0x3fc63ffb,0xbfffbec8,0x3fff3fed,0xbfa2bfed,0xbe493f44,0x3fc6bf44,
0x3f713fd5,0x3ff53f8e,0xbfe2bf8e,0xbf153fd5,0x3f8e0000,0x3ffb0000,0x3fd54000,0x3ec84000,0x3ffb3fed,0xbfd53f44,0xbec83f44,0xbf8ebfed,
0x3ec83fb5,0x3f8ebfb5,0xbffbbfb5,0x3fd53fb5,0xbfd5bf44,0xbec83fed,0xbf8ebfed,0xbffbbf44,0x3fff3fb5,0x3fc63fb5,0x3e493fb5,0xbfa23fb5,
0x3f153fd5,0xbfe2bf8e,0xbff5bf8e,0x3f71bfd5,0xbfe2bf44,0x3ff53f44,0xbf71bfed,0xbf153fed,0xbfa2bffb,0xbfffbec8,0x3fc63ec8,0x3e49bffb,
0x4000,0xbfb54000,0xc0000000,0xbfb50000,0xc000,0x3fb50000,0x40000000,0xbfb54000,0x4000,0x3fb5c000,0xc0000000,0x3fb50000,
0xc000,0xbfb50000,0x40000000,0x3fb5c000,0xbfc63fb5,0xbfff3fb5,0xbfa2bfb5,0x3e49bfb5,0x3fe2bf8e,0xbf153fd5,0x3f713fd5,0xbff53f8e,
0xbff53f44,0x3fe2bf44,0xbf15bfed,0xbf713fed,0x3fffbec8,0x3fa2bffb,0x3e493ffb,0x3fc6bec8,0xbffb0000,0xbf8e0000,0x3ec8c000,0x3fd5c000,
0x3fd53f44,0xbffb3fed,0xbf8e3fed,0xbec8bf44,0xbf8ebfb5,0xbec83fb5,0x3fd5bfb5,0xbffb3fb5,0x3ec83fed,0x3fd5bf44,0xbffb3f44,0xbf8e3fed,
0xbf71bfb5,0x3f15bfb5,0x3fe2bfb5,0x3ff5bfb5,0xbe493ffb,0xbfa23ec8,0xbfff3ec8,0x3fc6bffb,0x3fa2bfed,0xbfff3fed,0x3fc63f44,0xbe49bf44,
0xbff53f8e,0xbf713fd5,0xbf15bfd5,0xbfe23f8e,0x3f44c000,0x3fedc000,0x3fed0000,0x3f440000,0xbfed3fb5,0x3f44bfb5,0xbf44bfb5,0x3fedbfb5,
0x3fed0000,0xbf440000,0xbf444000,0x3fedc000,0xbf44bfb5,0xbfed3fb5,0x3fedbfb5,0x3f44bfb5,0x3ff5bfb5,0x3fe2bfb5,0x3f153fb5,0xbf713fb5,
0xbfc6bec8,0x3fffbffb,0x3fa2bffb,0x3e493ec8,0xbe493fed,0x3fc6bfed,0xbfff3f44,0x3fa2bf44,0x3fe2bfd5,0x3f15bf8e,0x3f713f8e,0x3ff5bfd5,
0x3fd50000,0x3ec80000,0xbf8e4000,0xbffb4000,0x3ec8bfed,0x3f8ebf44,0x3ffbbf44,0xbfd53fed,0xbffb3fb5,0x3fd5bfb5,0xbec8bfb5,0xbf8e3fb5,
0x3f8e3f44,0x3ffbbfed,0xbfd53fed,0xbec83f44,0x3e493fb5,0xbfa23fb5,0xbfff3fb5,0xbfc63fb5,0x3ff5bfd5,0xbf713f8e,0x3f153f8e,0xbfe23fd5,
0xbf71bf44,0xbf153f44,0x3fe2bfed,0xbff53fed,0xbfc63ffb,0xbe493ec8,0xbfa2bec8,0xbfff3ffb,0xc0004000,0xbfb54000,0x0,0x3fb50000,
0xc0004000,0x3fb50000,0x0,0x3fb5c000,0xc0004000,0x3fb5c000,0x0,0xbfb50000,0xc0004000,0xbfb50000,0x0,0xbfb54000,
0xbfa23fb5,0x3e493fb5,0x3fc6bfb5,0x3fffbfb5,0xbf713f8e,0x3ff5bfd5,0x3fe2bfd5,0xbf15bf8e,0xbf153f44,0xbf71bf44,0x3ff5bfed,0xbfe23fed,
0xbe493ec8,0xbfc63ffb,0x3fffbffb,0x3fa23ec8,0x3ec80000,0x3fd50000,0x3ffbc000,0x3f8ec000,0x3f8ebf44,0x3ec8bfed,0x3fd5bfed,0xbffb3f44,
0x3fd5bfb5,0xbffb3fb5,0x3f8ebfb5,0x3ec83fb5,0x3ffbbfed,0x3f8e3f44,0x3ec8bf44,0x3fd5bfed,0x3fe2bfb5,0x3ff5bfb5,0x3f71bfb5,0xbf15bfb5,
0x3fffbffb,0xbfc6bec8,0xbe49bec8,0xbfa23ffb,0x3fc6bfed,0xbe493fed,0xbfa23f44,0x3fffbf44,0x3f15bf8e,0x3fe2bfd5,0xbff53fd5,0xbf71bf8e,
0x3fedc000,0x3f44c000,0xbf440000,0xbfed0000,0x3f44bfb5,0xbfed3fb5,0xbfed3fb5,0x3f443fb5,0xbf440000,0x3fed0000,0xbfed4000,0x3f44c000,
0xbfed3fb5,0xbf44bfb5,0xbf443fb5,0xbfed3fb5,0x3f15bfb5,0xbf71bfb5,0xbff53fb5,0xbfe23fb5,0xbfa23ec8,0xbe493ffb,0xbfc63ffb,0x3fffbec8,
0xbfff3fed,0x3fa2bfed,0x3e493f44,0xbfc6bf44,0xbf713fd5,0xbff53f8e,0x3fe2bf8e,0x3f153fd5,0xbf8e0000,0xbffb0000,0xbfd54000,0xbec84000,
0xbffb3fed,0x3fd53f44,0x3ec83f44,0x3f8ebfed,0xbec83fb5,0xbf8ebfb5,0x3ffbbfb5,0xbfd53fb5,0x3fd5bf44,0x3ec83fed,0x3f8ebfed,0x3ffbbf44,
0xbfff3fb5,0xbfc63fb5,0xbe493fb5,0x3fa23fb5,0xbf153fd5,0x3fe2bf8e,0x3ff5bf8e,0xbf71bfd5,0x3fe2bf44,0xbff53f44,0x3f71bfed,0x3f153fed,
0x3fa2bffb,0x3fffbec8,0xbfc63ec8,0xbe49bffb,0x4000,0x3fb54000,0x40000000,0x3fb50000,0xc000,0xbfb50000,0xc0000000,0x3fb54000,
0x4000,0xbfb5c000,0x40000000,0xbfb50000,0xc000,0x3fb50000,0xc0000000,0xbfb5c000,0x3fc63fb5,0x3fff3fb5,0x3fa2bfb5,0xbe49bfb5,
0xbfe2bf8e,0x3f153fd5,0xbf713fd5,0x3ff53f8e,0x3ff53f44,0xbfe2bf44,0x3f15bfed,0x3f713fed,0xbfffbec8,0xbfa2bffb,0xbe493ffb,0xbfc6bec8,
0x3ffb0000,0x3f8e0000,0xbec8c000,0xbfd5c000,0xbfd53f44,0x3ffb3fed,0x3f8e3fed,0x3ec8bf44,0x3f8ebfb5,0x3ec83fb5,0xbfd5bfb5,0x3ffb3fb5,
0xbec83fed,0xbfd5bf44,0x3ffb3f44,0x3f8e3fed,0x3f71bfb5,0xbf15bfb5,0xbfe2bfb5,0xbff5bfb5,0x3e493ffb,0x3fa23ec8,0x3fff3ec8,0xbfc6bffb,
0xbfa2bfed,0x3fff3fed,0xbfc63f44,0x3e49bf44,0x3ff53f8e,0x3f713fd5,0x3f15bfd5,0x3fe23f8e,0xbf44c000,0xbfedc000,0xbfed0000,0xbf440000,
0x3fed3fb5,0xbf44bfb5,0x3f44bfb5,0xbfedbfb5,0xbfed0000,0x3f440000,0x3f444000,0xbfedc000,0x3f44bfb5,0x3fed3fb5,0xbfedbfb5,0xbf44bfb5,
0xbff5bfb5,0xbfe2bfb5,0xbf153fb5,0x3f713fb5,0x3fc6bec8,0xbfffbffb,0xbfa2bffb,0xbe493ec8,0x3e493fed,0xbfc6bfed,0x3fff3f44,0xbfa2bf44,
0xbfe2bfd5,0xbf15bf8e,0xbf713f8e,0xbff5bfd5,0xbfd50000,0xbec80000,0x3f8e4000,0x3ffb4000,0xbec8bfed,0xbf8ebf44,0xbffbbf44,0x3fd53fed,
0x3ffb3fb5,0xbfd5bfb5,0x3ec8bfb5,0x3f8e3fb5,0xbf8e3f44,0xbffbbfed,0x3fd53fed,0x3ec83f44,0xbe493fb5,0x3fa23fb5,0x3fff3fb5,0x3fc63fb5,
0xbff5bfd5,0x3f713f8e,0xbf153f8e,0x3fe23fd5,0x3f71bf44,0x3f153f44,0xbfe2bfed,0x3ff53fed,0x3fc63ffb,0x3e493ec8,0x3fa2bec8,0x3fff3ffb,
0x40004000,0x3fb54000,0x0,0xbfb50000,0x40004000,0xbfb50000,0x0,0xbfb5c000,0x40004000,0xbfb5c000,0x0,0x3fb50000,
0x40004000,0x3fb50000,0x0,0x3fb54000,0xbe490000,0xbfc60000,0xbfffc000,0xbfa2c000,0xbf15bec8,0xbf71bffb,0xbff5bffb,0x3fe23ec8,
0xbf71bf44,0x3ff53f44,0xbfe2bfed,0x3f153fed,0xbfa2bf8e,0x3e493fd5,0xbfc6bfd5,0xbfffbf8e,0xbffbc000,0xbf8ec000,0x3ec80000,0x3fd50000,
0xbfd5bfed,0x3ffb3f44,0x3f8e3f44,0x3ec83fed,0xbf8ebfb5,0xbec83fb5,0x3fd53fb5,0xbffbbfb5,0xbec8bf44,0xbfd5bfed,0x3ffb3fed,0x3f8ebf44,
0x3f150000,0x3fe20000,0x3ff54000,0x3f714000,0x3fc63f8e,0xbe493fd5,0x3fa23fd5,0xbfffbf8e,0x3fff3fed,0xbfc6bfed,0x3e493f44,0x3fa2bf44,
0x3fe23ffb,0x3ff53ec8,0xbf71bec8,0x3f153ffb,0x3fed4000,0x3f444000,0xbf440000,0xbfed0000,0x3f443fb5,0xbfedbfb5,0xbfedbfb5,0x3f44bfb5,
0xbf440000,0x3fed0000,0xbfedc000,0x3f444000,0xbfedbfb5,0xbf443fb5,0xbf44bfb5,0xbfedbfb5,0xbf710000,0xbff50000,0xbfe2c000,0xbf15c000,
0xbfffbfd5,0x3fa2bf8e,0xbe49bf8e,0x3fc63fd5,0xbfa2bfed,0xbe493fed,0x3fc63f44,0xbfffbf44,0x3f15bec8,0xbf71bffb,0x3ff53ffb,0x3fe2bec8,
0xbfd5c000,0xbec8c000,0x3f8e0000,0x3ffb0000,0x3ec8bf44,0x3f8e3fed,0x3ffb3fed,0xbfd53f44,0x3ffb3fb5,0xbfd5bfb5,0x3ec83fb5,0x3f8ebfb5,
0x3f8e3fed,0x3ffb3f44,0xbfd5bf44,0xbec83fed,0x3fa20000,0x3fff0000,0x3fc64000,0x3e494000,0x3fe23ffb,0xbff53ec8,0xbf713ec8,0xbf15bffb,
0xbf153f44,0x3fe2bf44,0xbff5bfed,0x3f713fed,0xbfffbfd5,0xbfc63f8e,0x3e49bf8e,0xbfa2bfd5,0x4000,0xbfb54000,0xc0000000,0xbfb50000,
0xc000,0x3fb50000,0x40000000,0xbfb54000,0x4000,0x3fb5c000,0xc0000000,0x3fb50000,0xc000,0xbfb50000,0x40000000,0x3fb5c000,
0xbfff0000,0xbfa20000,0x3e49c000,0x3fc6c000,0x3ff53ec8,0xbfe23ffb,0xbf153ffb,0xbf71bec8,0xbfe2bf44,0x3f153f44,0x3f71bfed,0xbff53fed,
0x3fc63f8e,0x3fffbfd5,0xbfa23fd5,0x3e493f8e,0x3ec8c000,0x3fd5c000,0x3ffb0000,0x3f8e0000,0xbf8e3fed,0xbec8bf44,0xbfd5bf44,0x3ffbbfed,
0x3fd5bfb5,0xbffb3fb5,0x3f8e3fb5,0x3ec8bfb5,0xbffb3f44,0xbf8e3fed,0xbec8bfed,0xbfd53f44,0x3ff50000,0x3f710000,0xbf154000,0xbfe24000,
0xbfa2bf8e,0x3fffbfd5,0x3fc6bfd5,0xbe493f8e,0x3e493fed,0x3fa2bfed,0xbfff3f44,0x3fc6bf44,0x3f71bffb,0xbf15bec8,0x3fe23ec8,0x3ff5bffb,
0xbf444000,0xbfed4000,0xbfed0000,0xbf440000,0x3fedbfb5,0xbf443fb5,0x3f443fb5,0xbfed3fb5,0xbfed0000,0x3f440000,0x3f44c000,0xbfed4000,
0x3f443fb5,0x3fedbfb5,0xbfed3fb5,0xbf443fb5,0xbfe20000,0xbf150000,0x3f71c000,0x3ff5c000,0x3e493fd5,0xbfc63f8e,0xbfff3f8e,0x3fa2bfd5,
0x3fc6bfed,0xbfff3fed,0x3fa23f44,0x3e49bf44,0xbff53ec8,0xbfe23ffb,0x3f15bffb,0xbf713ec8,0x3f8ec000,0x3ffbc000,0x3fd50000,0x3ec80000,
0xbffb3f44,0x3fd5bfed,0x3ec8bfed,0x3f8ebf44,0x3ec83fb5,0x3f8ebfb5,0xbffb3fb5,0x3fd5bfb5,0x3fd5bfed,0x3ec8bf44,0x3f8e3f44,0x3ffbbfed,
0x3fc60000,0x3e490000,0xbfa24000,0xbfff4000,0x3f71bffb,0x3f15bec8,0x3fe2bec8,0xbff53ffb,0xbff53f44,0x3f71bf44,0x3f15bfed,0xbfe23fed,
0xbe493fd5,0x3fa2bf8e,0xbfff3f8e,0xbfc63fd5,0xc0004000,0xbfb54000,0x0,0x3fb50000,0xc0004000,0x3fb50000,0x0,0x3fb5c000,
0xc0004000,0x3fb5c000,0x0,0xbfb50000,0xc0004000,0xbfb50000,0x0,0xbfb54000,0x3e490000,0x3fc60000,0x3fffc000,0x3fa2c000,
0x3f15bec8,0x3f71bffb,0x3ff5bffb,0xbfe23ec8,0x3f71bf44,0xbff53f44,0x3fe2bfed,0xbf153fed,0x3fa2bf8e,0xbe493fd5,0x3fc6bfd5,0x3fffbf8e,
0x3ffbc000,0x3f8ec000,0xbec80000,0xbfd50000,0x3fd5bfed,0xbffb3f44,0xbf8e3f44,0xbec83fed,0x3f8ebfb5,0x3ec83fb5,0xbfd53fb5,0x3ffbbfb5,
0x3ec8bf44,0x3fd5bfed,0xbffb3fed,0xbf8ebf44,0xbf150000,0xbfe20000,0xbff54000,0xbf714000,0xbfc63f8e,0x3e493fd5,0xbfa23fd5,0x3fffbf8e,
0xbfff3fed,0x3fc6bfed,0xbe493f44,0xbfa2bf44,0xbfe23ffb,0xbff53ec8,0x3f71bec8,0xbf153ffb,0xbfed4000,0xbf444000,0x3f440000,0x3fed0000,
0xbf443fb5,0x3fedbfb5,0x3fedbfb5,0xbf44bfb5,0x3f440000,0xbfed0000,0x3fedc000,0xbf444000,0x3fedbfb5,0x3f443fb5,0x3f44bfb5,0x3fedbfb5,
0x3f710000,0x3ff50000,0x3fe2c000,0x3f15c000,0x3fffbfd5,0xbfa2bf8e,0x3e49bf8e,0xbfc63fd5,0x3fa2bfed,0x3e493fed,0xbfc63f44,0x3fffbf44,
0xbf15bec8,0x3f71bffb,0xbff53ffb,0xbfe2bec8,0x3fd5c000,0x3ec8c000,0xbf8e0000,0xbffb0000,0xbec8bf44,0xbf8e3fed,0xbffb3fed,0x3fd53f44,
0xbffb3fb5,0x3fd5bfb5,0xbec83fb5,0xbf8ebfb5,0xbf8e3fed,0xbffb3f44,0x3fd5bf44,0x3ec83fed,0xbfa20000,0xbfff0000,0xbfc64000,0xbe494000,
0xbfe23ffb,0x3ff53ec8,0x3f713ec8,0x3f15bffb,0x3f153f44,0xbfe2bf44,0x3ff5bfed,0xbf713fed,0x3fffbfd5,0x3fc63f8e,0xbe49bf8e,0x3fa2bfd5,
0x4000,0x3fb54000,0x40000000,0x3fb50000,0xc000,0xbfb50000,0xc0000000,0x3fb54000,0x4000,0xbfb5c000,0x40000000,0xbfb50000,
0xc000,0x3fb50000,0xc0000000,0xbfb5c000,0x3fff0000,0x3fa20000,0xbe49c000,0xbfc6c000,0xbff53ec8,0x3fe23ffb,0x3f153ffb,0x3f71bec8,
0x3fe2bf44,0xbf153f44,0xbf71bfed,0x3ff53fed,0xbfc63f8e,0xbfffbfd5,0x3fa23fd5,0xbe493f8e,0xbec8c000,0xbfd5c000,0xbffb0000,0xbf8e0000,
0x3f8e3fed,0x3ec8bf44,0x3fd5bf44,0xbffbbfed,0xbfd5bfb5,0x3ffb3fb5,0xbf8e3fb5,0xbec8bfb5,0x3ffb3f44,0x3f8e3fed,0x3ec8bfed,0x3fd53f44,
0xbff50000,0xbf710000,0x3f154000,0x3fe24000,0x3fa2bf8e,0xbfffbfd5,0xbfc6bfd5,0x3e493f8e,0xbe493fed,0xbfa2bfed,0x3fff3f44,0xbfc6bf44,
0xbf71bffb,0x3f15bec8,0xbfe23ec8,0xbff5bffb,0x3f444000,0x3fed4000,0x3fed0000,0x3f440000,0xbfedbfb5,0x3f443fb5,0xbf443fb5,0x3fed3fb5,
0x3fed0000,0xbf440000,0xbf44c000,0x3fed4000,0xbf443fb5,0xbfedbfb5,0x3fed3fb5,0x3f443fb5,0x3fe20000,0x3f150000,0xbf71c000,0xbff5c000,
0xbe493fd5,0x3fc63f8e,0x3fff3f8e,0xbfa2bfd5,0xbfc6bfed,0x3fff3fed,0xbfa23f44,0xbe49bf44,0x3ff53ec8,0x3fe23ffb,0xbf15bffb,0x3f713ec8,
0xbf8ec000,0xbffbc000,0xbfd50000,0xbec80000,0x3ffb3f44,0xbfd5bfed,0xbec8bfed,0xbf8ebf44,0xbec83fb5,0xbf8ebfb5,0x3ffb3fb5,0xbfd5bfb5,
0xbfd5bfed,0xbec8bf44,0xbf8e3f44,0xbffbbfed,0xbfc60000,0xbe490000,0x3fa24000,0x3fff4000,0xbf71bffb,0xbf15bec8,0xbfe2bec8,0x3ff53ffb,
0x3ff53f44,0xbf71bf44,0xbf15bfed,0x3fe23fed,0x3e493fd5,0xbfa2bf8e,0x3fff3f8e,0x3fc63fd5,0x40004000,0x3fb54000,0x0,0xbfb50000,
0x40004000,0xbfb50000,0x0,0xbfb5c000,0x40004000,0xbfb5c000,0x0,0x3fb50000,0x40004000,0x3fb50000,0x0,0x3fb54000,
0xbfc6bfb5,0xbfffbfb5,0xbfa2bfb5,0x3e49bfb5,0xbfe2bfd5,0x3f15bf8e,0xbf71bf8e,0x3ff53fd5,0xbff5bfed,0x3fe23fed,0xbf15bf44,0xbf713f44,
0xbfffbffb,0xbfa23ec8,0xbe49bec8,0xbfc6bffb,0x3ec80000,0x3fd50000,0x3ffb4000,0x3f8e4000,0x3f8e3f44,0x3ec83fed,0x3fd53fed,0xbffbbf44,
0x3fd53fb5,0xbffbbfb5,0x3f8e3fb5,0x3ec8bfb5,0x3ffb3fed,0x3f8ebf44,0x3ec83f44,0x3fd53fed,0x3f713fb5,0xbf153fb5,0xbfe2bfb5,0xbff5bfb5,
0xbe493ec8,0xbfa2bffb,0xbfffbffb,0x3fc6bec8,0xbfa2bf44,0x3fff3f44,0xbfc6bfed,0x3e493fed,0xbff5bfd5,0xbf713f8e,0xbf15bf8e,0xbfe2bfd5,
0xbfedc000,0xbf44c000,0x3f440000,0x3fed0000,0xbf44bfb5,0x3fed3fb5,0x3fed3fb5,0xbf443fb5,0x3f440000,0xbfed0000,0x3fed4000,0xbf44c000,
0x3fed3fb5,0x3f44bfb5,0x3f443fb5,0x3fed3fb5,0x3ff53fb5,0x3fe23fb5,0x3f153fb5,0xbf713fb5,0x3fc63ffb,0xbfffbec8,0xbfa2bec8,0xbe49bffb,
0xbe493f44,0x3fc6bf44,0xbfffbfed,0x3fa23fed,0xbfe2bf8e,0xbf153fd5,0xbf71bfd5,0xbff5bf8e,0xbf8e0000,0xbffb0000,0xbfd5c000,0xbec8c000,
0xbffbbfed,0x3fd5bf44,0x3ec8bf44,0x3f8e3fed,0xbec8bfb5,0xbf8e3fb5,0x3ffb3fb5,0xbfd5bfb5,0x3fd53f44,0x3ec8bfed,0x3f8e3fed,0x3ffb3f44,
0xbe49bfb5,0x3fa2bfb5,0x3fff3fb5,0x3fc63fb5,0x3ff53f8e,0xbf713fd5,0x3f153fd5,0xbfe2bf8e,0x3f713fed,0x3f15bfed,0xbfe2bf44,0x3ff53f44,
0xbfc6bec8,0xbe493ffb,0xbfa2bffb,0xbfffbec8,0x4000,0xbfb54000,0xc0000000,0xbfb50000,0xc000,0x3fb50000,0x40000000,0xbfb54000,
0x4000,0x3fb5c000,0xc0000000,0x3fb50000,0xc000,0xbfb50000,0x40000000,0x3fb5c000,0xbfa2bfb5,0x3e49bfb5,0x3fc6bfb5,0x3fffbfb5,
0x3f713fd5,0xbff53f8e,0xbfe23f8e,0x3f15bfd5,0xbf15bfed,0xbf713fed,0x3ff5bf44,0xbfe23f44,0x3e493ffb,0x3fc6bec8,0xbfff3ec8,0xbfa23ffb,
0x3ffb0000,0x3f8e0000,0xbec84000,0xbfd54000,0xbfd5bf44,0x3ffbbfed,0x3f8ebfed,0x3ec83f44,0x3f8e3fb5,0x3ec8bfb5,0xbfd53fb5,0x3ffbbfb5,
0xbec8bfed,0xbfd53f44,0x3ffbbf44,0x3f8ebfed,0xbfe23fb5,0xbff53fb5,0xbf71bfb5,0x3f15bfb5,0x3fffbec8,0xbfc63ffb,0xbe493ffb,0xbfa23ec8,
0xbfc6bf44,0x3e493f44,0x3fa2bfed,0xbfff3fed,0x3f153fd5,0x3fe2bf8e,0xbff53f8e,0xbf713fd5,0x3f44c000,0x3fedc000,0x3fed0000,0x3f440000,
0xbfed3fb5,0x3f44bfb5,0xbf44bfb5,0x3fedbfb5,0x3fed0000,0xbf440000,0xbf444000,0x3fedc000,0xbf44bfb5,0xbfed3fb5,0x3fedbfb5,0x3f44bfb5,
0x3f153fb5,0xbf713fb5,0xbff53fb5,0xbfe23fb5,0x3fa2bffb,0x3e493ec8,0x3fc63ec8,0xbfff3ffb,0xbfff3f44,0x3fa2bf44,0x3e49bfed,0xbfc63fed,
0x3f713f8e,0x3ff5bfd5,0xbfe23fd5,0xbf153f8e,0xbfd50000,0xbec80000,0x3f8ec000,0x3ffbc000,0xbec83fed,0xbf8e3f44,0xbffb3f44,0x3fd5bfed,
0x3ffbbfb5,0xbfd53fb5,0x3ec83fb5,0x3f8ebfb5,0xbf8ebf44,0xbffb3fed,0x3fd5bfed,0x3ec8bf44,0x3fffbfb5,0x3fc6bfb5,0x3e493fb5,0xbfa23fb5,
0xbf15bf8e,0x3fe2bfd5,0x3ff5bfd5,0xbf713f8e,0xbfe23fed,0x3ff5bfed,0xbf71bf44,0xbf153f44,0x3fa23ec8,0x3fffbffb,0xbfc63ffb,0xbe493ec8,
0xc0004000,0xbfb54000,0x0,0x3fb50000,0xc0004000,0x3fb50000,0x0,0x3fb5c000,0xc0004000,0x3fb5c000,0x0,0xbfb50000,
0xc0004000,0xbfb50000,0x0,0xbfb54000,0x3fc6bfb5,0x3fffbfb5,0x3fa2bfb5,0xbe49bfb5,0x3fe2bfd5,0xbf15bf8e,0x3f71bf8e,0xbff53fd5,
0x3ff5bfed,0xbfe23fed,0x3f15bf44,0x3f713f44,0x3fffbffb,0x3fa23ec8,0x3e49bec8,0x3fc6bffb,0xbec80000,0xbfd50000,0xbffb4000,0xbf8e4000,
0xbf8e3f44,0xbec83fed,0xbfd53fed,0x3ffbbf44,0xbfd53fb5,0x3ffbbfb5,0xbf8e3fb5,0xbec8bfb5,0xbffb3fed,0xbf8ebf44,0xbec83f44,0xbfd53fed,
0xbf713fb5,0x3f153fb5,0x3fe2bfb5,0x3ff5bfb5,0x3e493ec8,0x3fa2bffb,0x3fffbffb,0xbfc6bec8,0x3fa2bf44,0xbfff3f44,0x3fc6bfed,0xbe493fed,
0x3ff5bfd5,0x3f713f8e,0x3f15bf8e,0x3fe2bfd5,0x3fedc000,0x3f44c000,0xbf440000,0xbfed0000,0x3f44bfb5,0xbfed3fb5,0xbfed3fb5,0x3f443fb5,
0xbf440000,0x3fed0000,0xbfed4000,0x3f44c000,0xbfed3fb5,0xbf44bfb5,0xbf443fb5,0xbfed3fb5,0xbff53fb5,0xbfe23fb5,0xbf153fb5,0x3f713fb5,
0xbfc63ffb,0x3fffbec8,0x3fa2bec8,0x3e49bffb,0x3e493f44,0xbfc6bf44,0x3fffbfed,0xbfa23fed,0x3fe2bf8e,0x3f153fd5,0x3f71bfd5,0x3ff5bf8e,
0x3f8e0000,0x3ffb0000,0x3fd5c000,0x3ec8c000,0x3ffbbfed,0xbfd5bf44,0xbec8bf44,0xbf8e3fed,0x3ec8bfb5,0x3f8e3fb5,0xbffb3fb5,0x3fd5bfb5,
0xbfd53f44,0xbec8bfed,0xbf8e3fed,0xbffb3f44,0x3e49bfb5,0xbfa2bfb5,0xbfff3fb5,0xbfc63fb5,0xbff53f8e,0x3f713fd5,0xbf153fd5,0x3fe2bf8e,
0xbf713fed,0xbf15bfed,0x3fe2bf44,0xbff53f44,0x3fc6bec8,0x3e493ffb,0x3fa2bffb,0x3fffbec8,0x4000,0x3fb54000,0x40000000,0x3fb50000,
0xc000,0xbfb50000,0xc0000000,0x3fb54000,0x4000,0xbfb5c000,0x40000000,0xbfb50000,0xc000,0x3fb50000,0xc0000000,0xbfb5c000,
0x3fa2bfb5,0xbe49bfb5,0xbfc6bfb5,0xbfffbfb5,0xbf713fd5,0x3ff53f8e,0x3fe23f8e,0xbf15bfd5,0x3f15bfed,0x3f713fed,0xbff5bf44,0x3fe23f44,
0xbe493ffb,0xbfc6bec8,0x3fff3ec8,0x3fa23ffb,0xbffb0000,0xbf8e0000,0x3ec84000,0x3fd54000,0x3fd5bf44,0xbffbbfed,0xbf8ebfed,0xbec83f44,
0xbf8e3fb5,0xbec8bfb5,0x3fd53fb5,0xbffbbfb5,0x3ec8bfed,0x3fd53f44,0xbffbbf44,0xbf8ebfed,0x3fe23fb5,0x3ff53fb5,0x3f71bfb5,0xbf15bfb5,
0xbfffbec8,0x3fc63ffb,0x3e493ffb,0x3fa23ec8,0x3fc6bf44,0xbe493f44,0xbfa2bfed,0x3fff3fed,0xbf153fd5,0xbfe2bf8e,0x3ff53f8e,0x3f713fd5,
0xbf44c000,0xbfedc000,0xbfed0000,0xbf440000,0x3fed3fb5,0xbf44bfb5,0x3f44bfb5,0xbfedbfb5,0xbfed0000,0x3f440000,0x3f444000,0xbfedc000,
0x3f44bfb5,0x3fed3fb5,0xbfedbfb5,0xbf44bfb5,0xbf153fb5,0x3f713fb5,0x3ff53fb5,0x3fe23fb5,0xbfa2bffb,0xbe493ec8,0xbfc63ec8,0x3fff3ffb,
0x3fff3f44,0xbfa2bf44,0xbe49bfed,0x3fc63fed,0xbf713f8e,0xbff5bfd5,0x3fe23fd5,0x3f153f8e,0x3fd50000,0x3ec80000,0xbf8ec000,0xbffbc000,
0x3ec83fed,0x3f8e3f44,0x3ffb3f44,0xbfd5bfed,0xbffbbfb5,0x3fd53fb5,0xbec83fb5,0xbf8ebfb5,0x3f8ebf44,0x3ffb3fed,0xbfd5bfed,0xbec8bf44,
0xbfffbfb5,0xbfc6bfb5,0xbe493fb5,0x3fa23fb5,0x3f15bf8e,0xbfe2bfd5,0xbff5bfd5,0x3f713f8e,0x3fe23fed,0xbff5bfed,0x3f71bf44,0x3f153f44,
0xbfa23ec8,0xbfffbffb,0x3fc63ffb,0x3e493ec8,0x80003f80,0x3f800000,0x80003f80,0x3f800000,0x80003f80,0x3f800000,0x80003f80,0x3f800000,
0x80003f80,0x3f800000,0x80003f80,0x3f800000,0x80003f80,0x3f800000,0x80003f80,0x3f800000,0x80003f80,0x3f800000,0x8000bf80,0xbf800000,
0x3f353f35,0x3f35bf35,0xbf35bf35,0xbf353f35,0x3f800000,0xbf80,0xbf800000,0x3f80,0x3f35bf35,0xbf35bf35,0xbf353f35,0x3f353f35,
0x80003f80,0x3f800000,0x80003f80,0x3f800000,0x3f800000,0xbf80,0x3f800000,0xbf80,0x8000bf80,0xbf800000,0x8000bf80,0xbf800000,
0xbf800000,0x3f80,0xbf800000,0x3f80,0x80003f80,0x3f800000,0x8000bf80,0xbf800000,0x3f35bf35,0xbf35bf35,0xbf353f35,0x3f353f35,
0xbf800000,0x3f80,0x3f800000,0xbf80,0x3f353f35,0x3f35bf35,0xbf35bf35,0xbf353f35,0x80003f80,0x3f800000,0x80003f80,0x3f800000,
0x8000bf80,0xbf800000,0x8000bf80,0xbf800000,0x80003f80,0x3f800000,0x80003f80,0x3f800000,0x8000bf80,0xbf800000,0x8000bf80,0xbf800000,
0x80003f80,0x3f800000,0x8000bf80,0xbf800000,0xbf35bf35,0xbf353f35,0x3f353f35,0x3f35bf35,0x3f800000,0xbf80,0xbf800000,0x3f80,
0xbf353f35,0x3f353f35,0x3f35bf35,0xbf35bf35,0x80003f80,0x3f800000,0x80003f80,0x3f800000,0xbf800000,0x3f80,0xbf800000,0x3f80,
0x8000bf80,0xbf800000,0x8000bf80,0xbf800000,0x3f800000,0xbf80,0x3f800000,0xbf80,0x80003f80,0x3f800000,0x8000bf80,0xbf800000,
0xbf353f35,0x3f353f35,0x3f35bf35,0xbf35bf35,0xbf800000,0x3f80,0x3f800000,0xbf80,0xbf35bf35,0xbf353f35,0x3f353f35,0x3f35bf35,
0x3f803f80,0x80008000,0x80008000,0xbf80bf80,0x3f803f80,0x80008000,0x80008000,0xbf80bf80,0x3f803f80,0x80008000,0x80008000,0xbf80bf80,
0x3f803f80,0x80008000,0x80008000,0xbf80bf80,0x3f353f80,0x3f358000,0x3f358000,0xbf35bf80,0xbf350000,0x3f353f80,0x3f353f80,0x3f358000,
0xbf35bf80,0xbf358000,0xbf358000,0x3f353f80,0x3f350000,0xbf35bf80,0xbf35bf80,0xbf358000,0x3f80,0x3f808000,0x3f808000,0x8000bf80,
0xbf80,0xbf808000,0xbf808000,0x80003f80,0x3f80,0x3f808000,0x3f808000,0x8000bf80,0xbf80,0xbf808000,0xbf808000,0x80003f80,
0xbf353f80,0x3f358000,0x3f358000,0x3f35bf80,0x3f350000,0x3f35bf80,0x3f35bf80,0xbf358000,0x3f35bf80,0xbf358000,0xbf358000,0xbf353f80,
0xbf350000,0xbf353f80,0xbf353f80,0x3f358000,0xbf803f80,0x80008000,0x80008000,0x3f80bf80,0xbf803f80,0x80008000,0x80008000,0x3f80bf80,
0xbf803f80,0x80008000,0x80008000,0x3f80bf80,0xbf803f80,0x80008000,0x80008000,0x3f80bf80,0xbf353f80,0xbf358000,0xbf358000,0x3f35bf80,
0x3f350000,0xbf353f80,0xbf353f80,0xbf358000,0x3f35bf80,0x3f358000,0x3f358000,0xbf353f80,0xbf350000,0x3f35bf80,0x3f35bf80,0x3f358000,
0x3f80,0xbf808000,0xbf808000,0x8000bf80,0xbf80,0x3f808000,0x3f808000,0x80003f80,0x3f80,0xbf808000,0xbf808000,0x8000bf80,
0xbf80,0x3f808000,0x3f808000,0x80003f80,0x3f353f80,0xbf358000,0xbf358000,0xbf35bf80,0xbf350000,0xbf35bf80,0xbf35bf80,0x3f358000,
0xbf35bf80,0x3f358000,0x3f358000,0x3f353f80,0x3f350000,0x3f353f80,0x3f353f80,0xbf358000,0x3f800000,0x0,0x3f800000,0x0,
0x3f800000,0x0,0x3f800000,0x0,0x3f800000,0x0,0x3f800000,0x0,0x3f800000,0x0,0x3f800000,0x0,
0x3f800000,0x0,0x3f7fb10f,0xbd48fb30,0x3f7ec46d,0xbdc8bd36,0x3f7d3aac,0xbe164083,0x3f7b14be,0xbe47c5c2,0x3f7853f8,0xbe78cfcc,
0x3f74fa0b,0xbe94a031,0x3f710908,0xbeac7cd4,0x3f800000,0x0,0x3f7ec46d,0xbdc8bd36,0x3f7b14be,0xbe47c5c2,0x3f74fa0b,0xbe94a031,
0x3f6c835e,0xbec3ef15,0x3f61c598,0xbef15aea,0x3f54db31,0xbf0e39da,0x3f45e403,0xbf226799,0x3f800000,0x0,0x3f7d3aac,0xbe164083,
0x3f74fa0b,0xbe94a031,0x3f676bd8,0xbedae880,0x3f54db31,0xbf0e39da,0x3f3daef9,0xbf2beb4a,0x3f226799,0xbf45e403,0x3f039c3d,0xbf5b941a,
0x3f800000,0x0,0x3f7b14be,0xbe47c5c2,0x3f6c835e,0xbec3ef15,0x3f54db31,0xbf0e39da,0x3f3504f3,0xbf3504f3,0x3f0e39da,0xbf54db31,
0x3ec3ef15,0xbf6c835e,0x3e47c5c2,0xbf7b14be,0x3f800000,0x0,0x3f7853f8,0xbe78cfcc,0x3f61c598,0xbef15aea,0x3f3daef9,0xbf2beb4a,
0x3f0e39da,0xbf54db31,0x3eac7cd4,0xbf710908,0x3dc8bd36,0xbf7ec46d,0xbe164083,0xbf7d3aac,0x3f800000,0x0,0x3f74fa0b,0xbe94a031,
0x3f54db31,0xbf0e39da,0x3f226799,0xbf45e403,0x3ec3ef15,0xbf6c835e,0x3dc8bd36,0xbf7ec46d,0xbe47c5c2,0xbf7b14be,0xbef15aea,0xbf61c598,
0x3f800000,0x0,0x3f710908,0xbeac7cd4,0x3f45e403,0xbf226799,0x3f039c3d,0xbf5b941a,0x3e47c5c2,0xbf7b14be,0xbe164083,0xbf7d3aac,
0xbef15aea,0xbf61c598,0xbf3daef9,0xbf2beb4a,0x3f800000,0x0,0x3f800000,0x0,0x3f800000,0x0,0x3f800000,0x0,
0x3f800000,0x0,0x3f800000,0x0,0x3f800000,0x0,0x3f800000,0x0,0x3f6c835e,0xbec3ef15,0x3f676bd8,0xbedae880,
0x3f61c598,0xbef15aea,0x3f5b941a,0xbf039c3d,0x3f54db31,0xbf0e39da,0x3f4d9f02,0xbf187fc0,0x3f45e403,0xbf226799,0x3f3daef9,0xbf2beb4a,
0x3f3504f3,0xbf3504f3,0x3f226799,0xbf45e403,0x3f0e39da,0xbf54db31,0x3ef15aea,0xbf61c598,0x3ec3ef15,0xbf6c835e,0x3e94a031,0xbf74fa0b,
0x3e47c5c2,0xbf7b14be,0x3dc8bd36,0xbf7ec46d,0x3ec3ef15,0xbf6c835e,0x3e78cfcc,0xbf7853f8,0x3dc8bd36,0xbf7ec46d,0xbd48fb30,0xbf7fb10f,
0xbe47c5c2,0xbf7b14be,0xbeac7cd4,0xbf710908,0xbef15aea,0xbf61c598,0xbf187fc0,0xbf4d9f02,0x0,0xbf800000,0xbe47c5c2,0xbf7b14be,
0xbec3ef15,0xbf6c835e,0xbf0e39da,0xbf54db31,0xbf3504f3,0xbf3504f3,0xbf54db31,0xbf0e39da,0xbf6c835e,0xbec3ef15,0xbf7b14be,0xbe47c5c2,
0xbec3ef15,0xbf6c835e,0xbf187fc0,0xbf4d9f02,0xbf45e403,0xbf226799,0xbf676bd8,0xbedae880,0xbf7b14be,0xbe47c5c2,0xbf7fb10f,0x3d48fb30,
0xbf74fa0b,0x3e94a031,0xbf5b941a,0x3f039c3d,0xbf3504f3,0xbf3504f3,0xbf61c598,0xbef15aea,0xbf7b14be,0xbe47c5c2,0xbf7ec46d,0x3dc8bd36,
0xbf6c835e,0x3ec3ef15,0xbf45e403,0x3f226799,0xbf0e39da,0x3f54db31,0xbe94a031,0x3f74fa0b,0xbf6c835e,0xbec3ef15,0xbf7fb10f,0xbd48fb30,
0xbf74fa0b,0x3e94a031,0xbf4d9f02,0x3f187fc0,0xbf0e39da,0x3f54db31,0xbe78cfcc,0x3f7853f8,0x3dc8bd36,0x3f7ec46d,0x3edae880,0x3f676bd8,
0x80003f80,0x3f800000,0x3f800000,0xbf80,0x3ec43f6d,0x3f6dbec4,0x3f6dbec4,0xbec4bf6d,0x3f353f35,0x3f35bf35,0x3f35bf35,0xbf35bf35,
0x3f6d3ec4,0x3ec4bf6d,0x3ec4bf6d,0xbf6dbec4,0x80003f80,0x3f800000,0xbf800000,0x3f80,0x3f6d3ec4,0x3ec4bf6d,0xbec43f6d,0x3f6d3ec4,
0x3f35bf35,0xbf35bf35,0x3f353f35,0x3f35bf35,0xbec4bf6d,0xbf6d3ec4,0x3f6dbec4,0xbec4bf6d,0x80003f80,0x3f800000,0x3f800000,0xbf80,
0x3f6dbec4,0xbec4bf6d,0xbec4bf6d,0xbf6d3ec4,0xbf35bf35,0xbf353f35,0xbf353f35,0x3f353f35,0xbec43f6d,0x3f6d3ec4,0x3f6d3ec4,0x3ec4bf6d,
0x80003f80,0x3f800000,0xbf800000,0x3f80,0x3ec4bf6d,0xbf6dbec4,0x3f6d3ec4,0x3ec4bf6d,0xbf353f35,0x3f353f35,0xbf35bf35,0xbf353f35,
0x3f6dbec4,0xbec4bf6d,0x3ec43f6d,0x3f6dbec4,0x80003f80,0x3f800000,0x3f800000,0xbf80,0xbec4bf6d,0xbf6d3ec4,0xbf6d3ec4,0x3ec43f6d,
0x3f353f35,0x3f35bf35,0x3f35bf35,0xbf35bf35,0xbf6dbec4,0xbec43f6d,0xbec43f6d,0x3f6d3ec4,0x80003f80,0x3f800000,0xbf800000,0x3f80,
0xbf6dbec4,0xbec43f6d,0x3ec4bf6d,0xbf6dbec4,0x3f35bf35,0xbf35bf35,0x3f353f35,0x3f35bf35,0x3ec43f6d,0x3f6dbec4,0xbf6d3ec4,0x3ec43f6d,
0x80003f80,0x3f800000,0x3f800000,0xbf80,0xbf6d3ec4,0x3ec43f6d,0x3ec43f6d,0x3f6dbec4,0xbf35bf35,0xbf353f35,0xbf353f35,0x3f353f35,
0x3ec4bf6d,0xbf6dbec4,0xbf6dbec4,0xbec43f6d,0x80003f80,0x3f800000,0xbf800000,0x3f80,0xbec43f6d,0x3f6d3ec4,0xbf6dbec4,0xbec43f6d,
0xbf353f35,0x3f353f35,0xbf35bf35,0xbf353f35,0xbf6d3ec4,0x3ec43f6d,0xbec4bf6d,0xbf6d3ec4,0x3f803f80,0x80008000,0x80008000,0xbf80bf80,
0x3f803f80,0x80008000,0x80008000,0xbf80bf80,0x3f803f80,0x80008000,0x80008000,0xbf80bf80,0x3f803f80,0x80008000,0x80008000,0xbf80bf80,
0x3ec43f6d,0x3f6d3ec4,0x3f6d3ec4,0xbec4bf6d,0xbf6dbec4,0x3ec43f6d,0x3ec43f6d,0x3f6d3ec4,0xbec4bf6d,0xbf6dbec4,0xbf6dbec4,0x3ec43f6d,
0x3f6d3ec4,0xbec4bf6d,0xbec4bf6d,0xbf6dbec4,0xbf353f35,0x3f353f35,0x3f353f35,0x3f35bf35,0x3f35bf35,0xbf35bf35,0xbf35bf35,0xbf353f35,
0xbf353f35,0x3f353f35,0x3f353f35,0x3f35bf35,0x3f35bf35,0xbf35bf35,0xbf35bf35,0xbf353f35,0xbf6d3ec4,0xbec43f6d,0xbec43f6d,0x3f6dbec4,
0xbec43f6d,0x3f6dbec4,0x3f6dbec4,0x3ec4bf6d,0x3f6dbec4,0x3ec4bf6d,0x3ec4bf6d,0xbf6d3ec4,0x3ec4bf6d,0xbf6d3ec4,0xbf6d3ec4,0xbec43f6d,
0x0,0xbf803f80,0xbf803f80,0x80008000,0x0,0xbf803f80,0xbf803f80,0x80008000,0x0,0xbf803f80,0xbf803f80,0x80008000,
0x0,0xbf803f80,0xbf803f80,0x80008000,0x3f6dbec4,0xbec43f6d,0xbec43f6d,0xbf6d3ec4,0x3ec4bf6d,0x3f6dbec4,0x3f6dbec4,0xbec43f6d,
0xbf6d3ec4,0x3ec4bf6d,0x3ec4bf6d,0x3f6dbec4,0xbec43f6d,0xbf6d3ec4,0xbf6d3ec4,0x3ec4bf6d,0x3f35bf35,0x3f353f35,0x3f353f35,0xbf353f35,
0xbf353f35,0xbf35bf35,0xbf35bf35,0x3f35bf35,0x3f35bf35,0x3f353f35,0x3f353f35,0xbf353f35,0xbf353f35,0xbf35bf35,0xbf35bf35,0x3f35bf35,
0xbec4bf6d,0x3f6d3ec4,0x3f6d3ec4,0x3ec43f6d,0x3f6d3ec4,0x3ec43f6d,0x3ec43f6d,0xbf6dbec4,0x3ec43f6d,0xbf6dbec4,0xbf6dbec4,0xbec4bf6d,
0xbf6dbec4,0xbec4bf6d,0xbec4bf6d,0x3f6d3ec4,0x3f800000,0x0,0x3f7fec43,0xbcc90ab0,0x3f7fb10f,0xbd48fb30,0x3f7f4e6d,0xbd96a905,
0x3f7ec46d,0xbdc8bd36,0x3f7e1324,0xbdfab273,0x3f7d3aac,0xbe164083,0x3f7c3b28,0xbe2f10a2,0x3f800000,0x0,0x3f7f4e6d,0xbd96a905,
0x3f7d3aac,0xbe164083,0x3f79c79d,0xbe605c13,0x3f74fa0b,0xbe94a031,0x3f6ed89e,0xbeb8442a,0x3f676bd8,0xbedae880,0x3f5ebe05,0xbefc5d27,
0x3f800000,0x0,0x3f7e1324,0xbdfab273,0x3f7853f8,0xbe78cfcc,0x3f6ed89e,0xbeb8442a,0x3f61c598,0xbef15aea,0x3f514d3d,0xbf13682a,
0x3f3daef9,0xbf2beb4a,0x3f273656,0xbf41d870,0x3f800000,0x0,0x3f7c3b28,0xbe2f10a2,0x3f710908,0xbeac7cd4,0x3f5ebe05,0xbefc5d27,
0x3f45e403,0xbf226799,0x3f273656,0xbf41d870,0x3f039c3d,0xbf5b941a,0x3eb8442a,0xbf6ed89e,0x3f800000,0x0,0x3f79c79d,0xbe605c13,
0x3f676bd8,0xbedae880,0x3f49d112,0xbf1d7fd1,0x3f226799,0xbf45e403,0x3ee63375,0xbf64aa59,0x3e78cfcc,0xbf7853f8,0x3cc90ab0,0xbf7fec43,
0x3f800000,0x0,0x3f76ba07,0xbe888e93,0x3f5b941a,0xbf039c3d,0x3f3085bb,0xbf396842,0x3ef15aea,0xbf61c598,0x3e605c13,0xbf79c79d,
0xbd48fb30,0xbf7fb10f,0xbea09ae5,0xbf731447,0x3f800000,0x0,0x3f731447,0xbea09ae5,0x3f4d9f02,0xbf187fc0,0x3f13682a,0xbf514d3d,
0x3e94a031,0xbf74fa0b,0xbcc90ab0,0xbf7fec43,0xbeac7cd4,0xbf710908,0xbf1d7fd1,0xbf49d112,0x3f800000,0x0,0x3f6ed89e,0xbeb8442a,
0x3f3daef9,0xbf2beb4a,0x3ee63375,0xbf64aa59,0x3dc8bd36,0xbf7ec46d,0xbe888e93,0xbf76ba07,0xbf187fc0,0xbf4d9f02,0xbf584853,0xbf08f59b,
0x3f7b14be,0xbe47c5c2,0x3f79c79d,0xbe605c13,0x3f7853f8,0xbe78cfcc,0x3f76ba07,0xbe888e93,0x3f74fa0b,0xbe94a031,0x3f731447,0xbea09ae5,
0x3f710908,0xbeac7cd4,0x3f6ed89e,0xbeb8442a,0x3f54db31,0xbf0e39da,0x3f49d112,0xbf1d7fd1,0x3f3daef9,0xbf2beb4a,0x3f3085bb,0xbf396842,
0x3f226799,0xbf45e403,0x3f13682a,0xbf514d3d,0x3f039c3d,0xbf5b941a,0x3ee63375,0xbf64aa59,0x3f0e39da,0xbf54db31,0x3ee63375,0xbf64aa59,
0x3eac7cd4,0xbf710908,0x3e605c13,0xbf79c79d,0x3dc8bd36,0xbf7ec46d,0xbcc90ab0,0xbf7fec43,0xbe164083,0xbf7d3aac,0xbe888e93,0xbf76ba07,
0x3e47c5c2,0xbf7b14be,0x3cc90ab0,0xbf7fec43,0xbe164083,0xbf7d3aac,0xbea09ae5,0xbf731447,0xbef15aea,0xbf61c598,0xbf1d7fd1,0xbf49d112,
0xbf3daef9,0xbf2beb4a,0xbf584853,0xbf08f59b,0xbe47c5c2,0xbf7b14be,0xbecf7bca,0xbf6a09a7,0xbf187fc0,0xbf4d9f02,0xbf41d870,0xbf273656,
0xbf61c598,0xbef15aea,0xbf76ba07,0xbe888e93,0xbf7fb10f,0xbd48fb30,0xbf7c3b28,0x3e2f10a2,0xbf0e39da,0xbf54db31,0xbf41d870,0xbf273656,
0xbf676bd8,0xbedae880,0xbf7c3b28,0xbe2f10a2,0xbf7ec46d,0x3dc8bd36,0xbf6ed89e,0x3eb8442a,0xbf4d9f02,0x3f187fc0,0xbf1d7fd1,0x3f49d112,
0xbf54db31,0xbf0e39da,0xbf76ba07,0xbe888e93,0xbf7fb10f,0x3d48fb30,0xbf6ed89e,0x3eb8442a,0xbf45e403,0x3f226799,0xbf08f59b,0x3f584853,
0xbe78cfcc,0x3f7853f8,0x3d96a905,0x3f7f4e6d,0xbf7b14be,0xbe47c5c2,0xbf7c3b28,0x3e2f10a2,0xbf5b941a,0x3f039c3d,0xbf1d7fd1,0x3f49d112,
0xbe94a031,0x3f74fa0b,0x3d96a905,0x3f7f4e6d,0x3edae880,0x3f676bd8,0x3f396842,0x3f3085bb,0x80003f80,0x80003f80,0x80003f80,0x80003f80,
0x80003f80,0x80003f80,0x80003f80,0x80003f80,0x80003f80,0x80003f80,0x80003f80,0x80003f80,0x80003f80,0x80003f80,0x80003f80,0x80003f80,
0x3f800000,0x3f800000,0x3f800000,0x3f800000,0x3f800000,0x3f800000,0x3f800000,0x3f800000,0x3f800000,0x3f800000,0x3f800000,0x3f800000,
0x3f800000,0x3f800000,0x3f800000,0x3f800000,0x80003f80,0x3f353f35,0x80003f80,0x3f353f35,0x3f800000,0x3f35bf35,0x3f800000,0x3f35bf35,
0x8000bf80,0xbf35bf35,0x8000bf80,0xbf35bf35,0xbf800000,0xbf353f35,0xbf800000,0xbf353f35,0x3f800000,0x3f35bf35,0x3f800000,0x3f35bf35,
0xbf80,0xbf35bf35,0xbf80,0xbf35bf35,0xbf800000,0xbf353f35,0xbf800000,0xbf353f35,0x3f80,0x3f353f35,0x3f80,0x3f353f35,
0x80003f80,0x3f800000,0x80003f80,0x3f800000,0x8000bf80,0xbf800000,0x8000bf80,0xbf800000,0x80003f80,0x3f800000,0x80003f80,0x3f800000,
0x8000bf80,0xbf800000,0x8000bf80,0xbf800000,0x3f800000,0xbf80,0x3f800000,0xbf80,0xbf800000,0x3f80,0xbf800000,0x3f80,
0x3f800000,0xbf80,0x3f800000,0xbf80,0xbf800000,0x3f80,0xbf800000,0x3f80,0x80003f80,0x3f35bf35,0x80003f80,0x3f35bf35,
0xbf800000,0x3f353f35,0xbf800000,0x3f353f35,0x8000bf80,0xbf353f35,0x8000bf80,0xbf353f35,0x3f800000,0xbf35bf35,0x3f800000,0xbf35bf35,
0x3f800000,0xbf35bf35,0x3f800000,0xbf35bf35,0x3f80,0x3f35bf35,0x3f80,0x3f35bf35,0xbf800000,0x3f353f35,0xbf800000,0x3f353f35,
0xbf80,0xbf353f35,0xbf80,0xbf353f35,0x80003f80,0x3ec43f6d,0x8000bf80,0xbec4bf6d,0x3f353f35,0x3f6d3ec4,0xbf35bf35,0xbf6dbec4,
0x3f800000,0x3f6dbec4,0xbf800000,0xbf6d3ec4,0x3f35bf35,0x3ec4bf6d,0xbf353f35,0xbec43f6d,0x3f800000,0x3f6dbec4,0xbf800000,0xbf6d3ec4,
0x3f35bf35,0x3ec4bf6d,0xbf353f35,0xbec43f6d,0xbf80,0xbec4bf6d,0x3f80,0x3ec43f6d,0xbf35bf35,0xbf6dbec4,0x3f353f35,0x3f6d3ec4,
0x80003f80,0x3f6d3ec4,0x8000bf80,0xbf6dbec4,0x3f35bf35,0xbec4bf6d,0xbf353f35,0x3ec43f6d,0xbf800000,0xbec43f6d,0x3f800000,0x3ec4bf6d,
0x3f353f35,0x3f6dbec4,0xbf35bf35,0xbf6d3ec4,0x3f800000,0x3ec4bf6d,0xbf800000,0xbec43f6d,0xbf35bf35,0xbf6d3ec4,0x3f353f35,0x3f6dbec4,
0x3f80,0x3f6d3ec4,0xbf80,0xbf6dbec4,0x3f35bf35,0xbec4bf6d,0xbf353f35,0x3ec43f6d,0x80003f80,0x3f6dbec4,0x8000bf80,0xbf6d3ec4,
0xbf35bf35,0xbec43f6d,0x3f353f35,0x3ec4bf6d,0x3f800000,0xbec4bf6d,0xbf800000,0x3ec43f6d,0xbf353f35,0x3f6d3ec4,0x3f35bf35,0xbf6dbec4,
0x3f800000,0xbec4bf6d,0xbf800000,0x3ec43f6d,0xbf353f35,0x3f6d3ec4,0x3f35bf35,0xbf6dbec4,0xbf80,0xbf6d3ec4,0x3f80,0x3f6dbec4,
0x3f353f35,0x3ec4bf6d,0xbf35bf35,0xbec43f6d,0x80003f80,0x3ec4bf6d,0x8000bf80,0xbec43f6d,0xbf353f35,0x3f6dbec4,0x3f35bf35,0xbf6d3ec4,
0xbf800000,0x3f6d3ec4,0x3f800000,0xbf6dbec4,0xbf35bf35,0x3ec43f6d,0x3f353f35,0xbec4bf6d,0x3f800000,0xbf6dbec4,0xbf800000,0x3f6d3ec4,
0x3f353f35,0xbec4bf6d,0xbf35bf35,0x3ec43f6d,0x3f80,0x3ec4bf6d,0xbf80,0xbec43f6d,0xbf353f35,0x3f6dbec4,0x3f35bf35,0xbf6d3ec4,
0x80003f80,0x8000bf80,0x80003f80,0x8000bf80,0x80003f80,0x8000bf80,0x80003f80,0x8000bf80,0x80003f80,0x8000bf80,0x80003f80,0x8000bf80,
0x80003f80,0x8000bf80,0x80003f80,0x8000bf80,0x3f800000,0xbf800000,0x3f800000,0xbf800000,0x3f800000,0xbf800000,0x3f800000,0xbf800000,
0x3f800000,0xbf800000,0x3f800000,0xbf800000,0x3f800000,0xbf800000,0x3f800000,0xbf800000,0x80003f80,0xbf35bf35,0x80003f80,0xbf35bf35,
0x3f800000,0xbf353f35,0x3f800000,0xbf353f35,0x8000bf80,0x3f353f35,0x8000bf80,0x3f353f35,0xbf800000,0x3f35bf35,0xbf800000,0x3f35bf35,
0x3f800000,0xbf353f35,0x3f800000,0xbf353f35,0xbf80,0x3f353f35,0xbf80,0x3f353f35,0xbf800000,0x3f35bf35,0xbf800000,0x3f35bf35,
0x3f80,0xbf35bf35,0x3f80,0xbf35bf35,0x80003f80,0xbf800000,0x80003f80,0xbf800000,0x8000bf80,0x3f800000,0x8000bf80,0x3f800000,
0x80003f80,0xbf800000,0x80003f80,0xbf800000,0x8000bf80,0x3f800000,0x8000bf80,0x3f800000,0x3f800000,0x3f80,0x3f800000,0x3f80,
0xbf800000,0xbf80,0xbf800000,0xbf80,0x3f800000,0x3f80,0x3f800000,0x3f80,0xbf800000,0xbf80,0xbf800000,0xbf80,
0x80003f80,0xbf353f35,0x80003f80,0xbf353f35,0xbf800000,0xbf35bf35,0xbf800000,0xbf35bf35,0x8000bf80,0x3f35bf35,0x8000bf80,0x3f35bf35,
0x3f800000,0x3f353f35,0x3f800000,0x3f353f35,0x3f800000,0x3f353f35,0x3f800000,0x3f353f35,0x3f80,0xbf353f35,0x3f80,0xbf353f35,
0xbf800000,0xbf35bf35,0xbf800000,0xbf35bf35,0xbf80,0x3f35bf35,0xbf80,0x3f35bf35,0x80003f80,0xbec4bf6d,0x8000bf80,0x3ec43f6d,
0x3f353f35,0xbf6dbec4,0xbf35bf35,0x3f6d3ec4,0x3f800000,0xbf6d3ec4,0xbf800000,0x3f6dbec4,0x3f35bf35,0xbec43f6d,0xbf353f35,0x3ec4bf6d,
0x3f800000,0xbf6d3ec4,0xbf800000,0x3f6dbec4,0x3f35bf35,0xbec43f6d,0xbf353f35,0x3ec4bf6d,0xbf80,0x3ec43f6d,0x3f80,0xbec4bf6d,
0xbf35bf35,0x3f6d3ec4,0x3f353f35,0xbf6dbec4,0x80003f80,0xbf6dbec4,0x8000bf80,0x3f6d3ec4,0x3f35bf35,0x3ec43f6d,0xbf353f35,0xbec4bf6d,
0xbf800000,0x3ec4bf6d,0x3f800000,0xbec43f6d,0x3f353f35,0xbf6d3ec4,0xbf35bf35,0x3f6dbec4,0x3f800000,0xbec43f6d,0xbf800000,0x3ec4bf6d,
0xbf35bf35,0x3f6dbec4,0x3f353f35,0xbf6d3ec4,0x3f80,0xbf6dbec4,0xbf80,0x3f6d3ec4,0x3f35bf35,0x3ec43f6d,0xbf353f35,0xbec4bf6d,
0x80003f80,0xbf6d3ec4,0x8000bf80,0x3f6dbec4,0xbf35bf35,0x3ec4bf6d,0x3f353f35,0xbec43f6d,0x3f800000,0x3ec43f6d,0xbf800000,0xbec4bf6d,
0xbf353f35,0xbf6dbec4,0x3f35bf35,0x3f6d3ec4,0x3f800000,0x3ec43f6d,0xbf800000,0xbec4bf6d,0xbf353f35,0xbf6dbec4,0x3f35bf35,0x3f6d3ec4,
0xbf80,0x3f6dbec4,0x3f80,0xbf6d3ec4,0x3f353f35,0xbec43f6d,0xbf35bf35,0x3ec4bf6d,0x80003f80,0xbec43f6d,0x8000bf80,0x3ec4bf6d,
0xbf353f35,0xbf6d3ec4,0x3f35bf35,0x3f6dbec4,0xbf800000,0xbf6dbec4,0x3f800000,0x3f6d3ec4,0xbf35bf35,0xbec4bf6d,0x3f353f35,0x3ec43f6d,
0x3f800000,0x3f6d3ec4,0xbf800000,0xbf6dbec4,0x3f353f35,0x3ec43f6d,0xbf35bf35,0xbec4bf6d,0x3f80,0xbec43f6d,0xbf80,0x3ec4bf6d,
0xbf353f35,0xbf6d3ec4,0x3f35bf35,0x3f6dbec4,
};
constexpr int TB_F = 0, TB_E = 512, TB_P2 = 1024;

enum { C_EP = 0, C_Z1 = 32, C_Z2 = 96, C_H3 = 128, C_U = 160, C_X = 256, C_TOTAL = 512 };
struct Scratch {
  unsigned cnt[C_TOTAL];
  uint32_t moda[8 * 2 * D_];
  uint32_t mod[4 * D_ + 256];
  uint32_t z1[120 * 5120];
  uint32_t z2[128 * 4800];
  uint8_t h3[32 * 18 * 4096];
  uint8_t u[72 * D_ * 128];
};
__device__ __align__(1024) Scratch g_s;

#define PF2 8
#define PF2K 16
#define HOLDA 5
#define GOAT 0
#define HW bulk_commit_wait
#define H3W 0
#define X1K 10
#define PEEK 1
#define H3G 1
#define PFF 2
#ifndef NV1
#define NV1 12
#endif
#ifndef NV2
#define NV2 20
#endif
#define GDEP 0
#define TRK0 50
#define W0N 3
#define TRKC 350
#define J2 6
#define NG1 2

#define FAILCNT(k) do {} while (0)
#define CK(k) do {} while (0)
#define CKX(k) do {} while (0)
#define TS(k) do {} while (0)
#define TSC(k) do {} while (0)
struct Maps { CUtensorMap z1, z2[2], w1a, w1b, h3[2], w2, wf[4], wm; };
struct Params {
  const __nv_bfloat16 *x, *c, *wmod;
  Scratch* s;
  const uint4* tab;
  const __nv_bfloat16 *wr, *wi, *w1, *w2, *b1, *b2;
  uint32_t* out;
};

__device__ __forceinline__ uint32_t smem_u32(const void* p) { return (uint32_t)__cvta_generic_to_shared(p); }
__device__ __forceinline__ void mbar_init(uint32_t b, int c) { asm volatile("mbarrier.init.shared::cta.b64 [%0], %1;" ::"r"(b), "r"(c)); }
__device__ __forceinline__ void mbar_expect(uint32_t b, int bytes) { asm volatile("mbarrier.arrive.expect_tx.shared::cta.b64 _, [%0], %1;" ::"r"(b), "r"(bytes) : "memory"); }
__device__ __forceinline__ void mbar_arrive(uint32_t b) { asm volatile("mbarrier.arrive.shared::cta.b64 _, [%0];" ::"r"(b) : "memory"); }
#define MBAR_WAIT(SEM)                                                                                                         \
  asm volatile("{\n.reg .pred p;\n.reg .u32 it;\nmov.u32 it, 0;\nW:\nmbarrier.try_wait.parity" SEM ".shared::cta.b64 p, [%0], %1;\n" \
               "@p bra.uni D;\nadd.u32 it, it, 1;\nsetp.lt.u32 p, it, 0x400000;\n@p bra.uni W;\ntrap;\nD:\n}" ::"r"(b), "r"(ph) : "memory")
__device__ __forceinline__ void mbar_wait(uint32_t b, int ph) { MBAR_WAIT(""); }
__device__ __forceinline__ uint32_t mbar_test(uint32_t b, int ph) {
  uint32_t ok;
  asm volatile("{\n.reg .pred p;\nmbarrier.test_wait.parity.shared::cta.b64 p, [%1], %2;\nselp.u32 %0, 1, 0, p;\n}\n" : "=r"(ok) : "r"(b), "r"(ph) : "memory");
  return ok;
}
__device__ __forceinline__ void tma2d(uint32_t dst, const CUtensorMap* m, int c0, int c1, uint32_t bar) {
  asm volatile("cp.async.bulk.tensor.2d.shared::cluster.global.mbarrier::complete_tx::bytes [%0], [%1, {%3, %4}], [%2];" ::"r"(dst), "l"(m), "r"(bar), "r"(c0), "r"(c1) : "memory");
}
__device__ __forceinline__ uint64_t pol_ef() { uint64_t p; asm("createpolicy.fractional.L2::evict_first.b64 %0, 1.0;" : "=l"(p)); return p; }
__device__ __forceinline__ void tma3d_ef(uint32_t dst, const CUtensorMap* m, int c1, int c2, uint32_t bar) {
  asm volatile("cp.async.bulk.tensor.3d.shared::cluster.global.mbarrier::complete_tx::bytes.L2::cache_hint [%0], [%1, {%3, %4, %5}], [%2], %6;" ::"r"(dst), "l"(m), "r"(bar), "r"(0), "r"(c1), "r"(c2), "l"(pol_ef()) : "memory");
}
__device__ __forceinline__ void tma4d_ef(uint32_t dst, const CUtensorMap* m, int c1, int c2, int c3, uint32_t bar) {
  asm volatile("cp.async.bulk.tensor.4d.shared::cluster.global.mbarrier::complete_tx::bytes.L2::cache_hint [%0], [%1, {%3, %7, %4, %5}], [%2], %6;" ::"r"(dst), "l"(m), "r"(bar), "r"(0), "r"(c2), "r"(c3), "l"(pol_ef()), "r"(c1) : "memory");
}
__device__ __forceinline__ void bulk_ld(uint32_t dst, const void* src, int bytes, uint32_t bar) {
  asm volatile("cp.async.bulk.shared::cluster.global.mbarrier::complete_tx::bytes [%0], [%1], %2, [%3];" ::"r"(dst), "l"(src), "r"(bytes), "r"(bar) : "memory");
}
__device__ __forceinline__ void bulk_st(void* dst, uint32_t src, int bytes) {
  asm volatile("cp.async.bulk.global.shared::cta.bulk_group [%0], [%1], %2;" ::"l"(dst), "r"(src), "r"(bytes) : "memory");
}
__device__ __forceinline__ void tma_st2d(const CUtensorMap* m, uint32_t src, int c0, int c1) {
  asm volatile("cp.async.bulk.tensor.2d.global.shared::cta.bulk_group [%0, {%2, %3}], [%1];" ::"l"(m), "r"(src), "r"(c0), "r"(c1) : "memory");
}
__device__ __forceinline__ void tma_st3d(const CUtensorMap* m, uint32_t src, int c0, int c1, int c2) {
  asm volatile("cp.async.bulk.tensor.3d.global.shared::cta.bulk_group [%0, {%2, %3, %4}], [%1];" ::"l"(m), "r"(src), "r"(c0), "r"(c1), "r"(c2) : "memory");
}
__device__ __forceinline__ void bulk_commit_wait_read() {
  asm volatile("cp.async.bulk.commit_group;" ::: "memory");
  asm volatile("cp.async.bulk.wait_group.read 0;" ::: "memory");
}
__device__ __forceinline__ void bulk_commit_wait() {
  asm volatile("cp.async.bulk.commit_group;" ::: "memory");
  asm volatile("cp.async.bulk.wait_group 0;" ::: "memory");
}
__device__ __forceinline__ void prefetch_l2(const void* p, int bytes) {
  asm volatile("cp.async.bulk.prefetch.L2.global [%0], %1;" ::"l"(p), "r"(bytes) : "memory");
}
__device__ __forceinline__ void wg_fence() { asm volatile("wgmma.fence.sync.aligned;" ::: "memory"); }
__device__ __forceinline__ void wg_commit() { asm volatile("wgmma.commit_group.sync.aligned;" ::: "memory"); }
template <int N> __device__ __forceinline__ void wg_wait() { asm volatile("wgmma.wait_group.sync.aligned %0;" ::"n"(N) : "memory"); }
template <int N> __device__ __forceinline__ void reg_fence(float (&d)[N]) {
#pragma unroll
  for (int i = 0; i < N; i++) asm volatile("" : "+f"(d[i])::"memory");
}
__device__ __forceinline__ void fence_async_smem() { asm volatile("fence.proxy.async.shared::cta;" ::: "memory"); }
__device__ __forceinline__ void fence_async_glb() { asm volatile("fence.proxy.async.global;" ::: "memory"); }
__device__ __forceinline__ uint32_t ld_rlx(const void* p) { uint32_t v; asm volatile("ld.relaxed.gpu.global.b32 %0, [%1];" : "=r"(v) : "l"(p) : "memory"); return v; }
__device__ __forceinline__ uint2 ld_rlx2(const void* p) { uint2 v; asm volatile("ld.relaxed.gpu.global.v2.b32 {%0,%1}, [%2];" : "=r"(v.x), "=r"(v.y) : "l"(p) : "memory"); return v; }
__device__ __forceinline__ uint4 ld_rlx4(const void* p) { uint4 v; asm volatile("ld.relaxed.gpu.global.v4.b32 {%0,%1,%2,%3}, [%4];" : "=r"(v.x), "=r"(v.y), "=r"(v.z), "=r"(v.w) : "l"(p) : "memory"); return v; }
__device__ __forceinline__ uint32_t ld_nc(const void* p) { uint32_t v; asm volatile("ld.global.nc.L1::no_allocate.b32 %0, [%1];" : "=r"(v) : "l"(p) : "memory"); return v; }
__device__ __forceinline__ uint4 ld_nc4(const void* p) { uint4 v; asm volatile("ld.global.nc.v4.b32 {%0,%1,%2,%3}, [%4];" : "=r"(v.x), "=r"(v.y), "=r"(v.z), "=r"(v.w) : "l"(p) : "memory"); return v; }
__device__ __forceinline__ uint32_t lds(uint32_t a) { uint32_t v; asm volatile("ld.shared.b32 %0, [%1];" : "=r"(v) : "r"(a) : "memory"); return v; }
__device__ __forceinline__ uint2 lds2(uint32_t a) { uint2 v; asm volatile("ld.shared.v2.b32 {%0,%1}, [%2];" : "=r"(v.x), "=r"(v.y) : "r"(a) : "memory"); return v; }
__device__ __forceinline__ uint4 lds4(uint32_t a) { uint4 v; asm volatile("ld.shared.v4.b32 {%0,%1,%2,%3}, [%4];" : "=r"(v.x), "=r"(v.y), "=r"(v.z), "=r"(v.w) : "r"(a) : "memory"); return v; }
__device__ __forceinline__ float lds_bf(uint32_t a) { uint32_t v; asm volatile("ld.shared.u16 %0, [%1];" : "=r"(v) : "r"(a) : "memory"); return __uint_as_float(v << 16); }
__device__ __forceinline__ void sts(uint32_t a, uint32_t v) { asm volatile("st.shared.b32 [%0], %1;" ::"r"(a), "r"(v) : "memory"); }
__device__ __forceinline__ void sts2(uint32_t a, uint32_t v0, uint32_t v1) { asm volatile("st.shared.v2.b32 [%0], {%1,%2};" ::"r"(a), "r"(v0), "r"(v1) : "memory"); }
__device__ __forceinline__ void sts4(uint32_t a, uint32_t v0, uint32_t v1, uint32_t v2, uint32_t v3) { asm volatile("st.shared.v4.b32 [%0], {%1,%2,%3,%4};" ::"r"(a), "r"(v0), "r"(v1), "r"(v2), "r"(v3) : "memory"); }
__device__ __forceinline__ void bar_sync(int id, int n) { asm volatile("bar.sync %0, %1;" ::"r"(id), "r"(n) : "memory"); }
__device__ __forceinline__ void bar_arrive(int id, int n) { asm volatile("bar.arrive %0, %1;" ::"r"(id), "r"(n) : "memory"); }
__device__ __forceinline__ void red_add(unsigned* p, unsigned v) { asm volatile("red.relaxed.gpu.global.add.u32 [%0], %1;" ::"l"(p), "r"(v) : "memory"); }
__device__ __forceinline__ bool any(bool p) { return __any_sync(0xffffffffu, p); }
__device__ __forceinline__ void pause(unsigned clks) {
  asm volatile("{\n.reg .pred p;\n.reg .u32 a, b;\nmov.u32 a, %%clock;\nW:\nmov.u32 b, %%clock;\nsub.u32 b, b, a;\nsetp.lt.s32 p, b, %0;\n@p bra.uni W;\n}" ::"r"(clks) : "memory");
}
__device__ __forceinline__ void red_bf16x8(uint32_t* p, uint32_t a, uint32_t b, uint32_t c, uint32_t d) {
  asm volatile("red.relaxed.gpu.global.add.noftz.v4.bf16x2 [%0], {%1,%2,%3,%4};" ::"l"(p), "r"(a), "r"(b), "r"(c), "r"(d) : "memory");
}
__device__ __forceinline__ void red_bf16x4(uint32_t* p, uint32_t a, uint32_t b) {
  asm volatile("red.relaxed.gpu.global.add.noftz.v2.bf16x2 [%0], {%1,%2};" ::"l"(p), "r"(a), "r"(b) : "memory");
}
constexpr int SPIN_MAX = 1 << 20;
__device__ __forceinline__ uint32_t ld_acq(const void* p) { uint32_t v; asm volatile("ld.acquire.gpu.global.b32 %0, [%1];" : "=r"(v) : "l"(p) : "memory"); return v; }
template <bool ACQ = false> __device__ __forceinline__ void wait_cnt(const unsigned* p, unsigned target) {
  int it = 0;
  while (any((int)((ACQ ? ld_acq(p) : ld_rlx(p)) - target) < 0) && ++it < SPIN_MAX) {}
}
__device__ __forceinline__ uint32_t pack_bf16(float lo, float hi) { uint32_t r; asm("cvt.rn.bf16x2.f32 %0, %1, %2;" : "=r"(r) : "f"(hi), "f"(lo)); return r; }
__device__ __forceinline__ float bf_lo(uint32_t v) { return __uint_as_float(v << 16); }
__device__ __forceinline__ float bf_hi(uint32_t v) { return __uint_as_float(v & 0xffff0000u); }
__device__ __forceinline__ uint32_t hadd2(uint32_t a, uint32_t b) { uint32_t r; asm("add.rn.bf16x2 %0, %1, %2;" : "=r"(r) : "r"(a), "r"(b)); return r; }
__device__ __forceinline__ uint32_t hmul2(uint32_t a, uint32_t b) { uint32_t r; asm("mul.rn.bf16x2 %0, %1, %2;" : "=r"(r) : "r"(a), "r"(b)); return r; }
__device__ __forceinline__ uint32_t hfma2(uint32_t a, uint32_t b, uint32_t c) { uint32_t r; asm("fma.rn.bf16x2 %0, %1, %2, %3;" : "=r"(r) : "r"(a), "r"(b), "r"(c)); return r; }
__device__ __forceinline__ float rbf(float x) { uint32_t r; asm("cvt.rn.bf16x2.f32 %0, %1, %2;" : "=r"(r) : "f"(x), "f"(0.0f)); return __uint_as_float(r); }
__device__ __forceinline__ void stmatrix4(uint32_t a, uint32_t r0, uint32_t r1, uint32_t r2, uint32_t r3) {
  asm volatile("stmatrix.sync.aligned.m8n8.x4.shared.b16 [%0], {%1,%2,%3,%4};" ::"r"(a), "r"(r0), "r"(r1), "r"(r2), "r"(r3) : "memory");
}
__device__ __forceinline__ void stmatrix2(uint32_t a, uint32_t r0, uint32_t r1) {
  asm volatile("stmatrix.sync.aligned.m8n8.x2.shared.b16 [%0], {%1,%2};" ::"r"(a), "r"(r0), "r"(r1) : "memory");
}
__device__ __forceinline__ void stmatrix4t(uint32_t a, uint32_t r0, uint32_t r1, uint32_t r2, uint32_t r3) {
  asm volatile("stmatrix.sync.aligned.m8n8.x4.trans.shared.b16 [%0], {%1,%2,%3,%4};" ::"r"(a), "r"(r0), "r"(r1), "r"(r2), "r"(r3) : "memory");
}
__device__ __forceinline__ uint32_t movm(uint32_t a) { uint32_t r; asm("movmatrix.sync.aligned.m8n8.trans.b16 %0, %1;" : "=r"(r) : "r"(a)); return r; }
template <bool ACC> __device__ __forceinline__ void mma16(float* d, uint32_t a0, uint32_t a1, uint32_t a2, uint32_t a3, uint32_t b0, uint32_t b1) {
  if (ACC) asm("mma.sync.aligned.m16n8k16.row.col.f32.bf16.bf16.f32 {%0,%1,%2,%3}, {%4,%5,%6,%7}, {%8,%9}, {%0,%1,%2,%3};"
               : "+f"(d[0]), "+f"(d[1]), "+f"(d[2]), "+f"(d[3]) : "r"(a0), "r"(a1), "r"(a2), "r"(a3), "r"(b0), "r"(b1));
  else asm("mma.sync.aligned.m16n8k16.row.col.f32.bf16.bf16.f32 {%0,%1,%2,%3}, {%4,%5,%6,%7}, {%8,%9}, {%10,%10,%10,%10};"
           : "=f"(d[0]), "=f"(d[1]), "=f"(d[2]), "=f"(d[3]) : "r"(a0), "r"(a1), "r"(a2), "r"(a3), "r"(b0), "r"(b1), "f"(0.f));
}
__device__ __forceinline__ uint32_t pin(uint32_t v) { uint32_t r; asm volatile("shfl.sync.bfly.b32 %0, %1, 0, 31, 0xffffffff;" : "=r"(r) : "r"(v)); return r; }
template <class T> __device__ __forceinline__ T* pin(T* p) {
  const uint64_t a = reinterpret_cast<uint64_t>(p);
  return reinterpret_cast<T*>((uint64_t)pin((uint32_t)a) | ((uint64_t)pin((uint32_t)(a >> 32)) << 32));
}
__device__ __forceinline__ uint32_t upin(uint32_t v) { return __shfl_sync(0xffffffffu, v, 0); }
template <class T> __device__ __forceinline__ T* upin(T* p) {
  const uint64_t a = reinterpret_cast<uint64_t>(p);
  return reinterpret_cast<T*>((uint64_t)upin((uint32_t)a) | ((uint64_t)upin((uint32_t)(a >> 32)) << 32));
}
__device__ __forceinline__ bool elect() {
  uint32_t p;
  asm volatile("{\n.reg .pred P;\nelect.sync _|P, 0xffffffff;\nselp.u32 %0, 1, 0, P;\n}" : "=r"(p));
  return p;
}
__device__ __forceinline__ uint32_t set_tag(uint32_t w, uint32_t tag) { uint32_t r; asm("lop3.b32 %0, %1, 0xfffffffe, %2, 0xea;" : "=r"(r) : "r"(w), "r"(tag)); return r; }
__device__ __forceinline__ uint32_t and_or(uint32_t w, uint32_t a, uint32_t o) { uint32_t r; asm("lop3.b32 %0, %1, %2, %3, 0xea;" : "=r"(r) : "r"(w), "r"(a), "r"(o)); return r; }
__device__ __forceinline__ uint32_t or3(uint32_t a, uint32_t b, uint32_t c) { uint32_t r; asm("lop3.b32 %0, %1, %2, %3, 0xfe;" : "=r"(r) : "r"(a), "r"(b), "r"(c)); return r; }
__device__ __forceinline__ uint32_t diff2(uint32_t a, uint32_t b, uint32_t tag) { uint32_t r; asm("lop3.b32 %0, %1, %2, %3, 0x7e;" : "=r"(r) : "r"(a), "r"(b), "r"(tag)); return r; }
__device__ __forceinline__ float2 cmul(float2 a, float2 b) { return make_float2(a.x * b.x - a.y * b.y, a.x * b.y + a.y * b.x); }

template<int TB> __device__ __forceinline__ void wgmma_ss_160_0(float (&d)[96], uint32_t al, uint32_t ah, uint32_t bl, uint32_t bh) {
  asm volatile("{\n.reg .b64 da, db;\nmov.b64 da, {%80, %81};\nmov.b64 db, {%82, %83};\n"
    "wgmma.mma_async.sync.aligned.m64n160k16.f32.bf16.bf16 {%0,%1,%2,%3,%4,%5,%6,%7,%8,%9,%10,%11,%12,%13,%14,%15,%16,%17,%18,%19,%20,%21,%22,%23,%24,%25,%26,%27,%28,%29,%30,%31,%32,%33,%34,%35,%36,%37,%38,%39,%40,%41,%42,%43,%44,%45,%46,%47,%48,%49,%50,%51,%52,%53,%54,%55,%56,%57,%58,%59,%60,%61,%62,%63,%64,%65,%66,%67,%68,%69,%70,%71,%72,%73,%74,%75,%76,%77,%78,%79}, da, db, 1, 1, 1, 1, %84;\n}\n"
    : "+f"(d[0]),"+f"(d[1]),"+f"(d[2]),"+f"(d[3]),"+f"(d[4]),"+f"(d[5]),"+f"(d[6]),"+f"(d[7]),"+f"(d[8]),"+f"(d[9]),"+f"(d[10]),"+f"(d[11]),"+f"(d[12]),"+f"(d[13]),"+f"(d[14]),"+f"(d[15]),"+f"(d[16]),"+f"(d[17]),"+f"(d[18]),"+f"(d[19]),"+f"(d[20]),"+f"(d[21]),"+f"(d[22]),"+f"(d[23]),"+f"(d[24]),"+f"(d[25]),"+f"(d[26]),"+f"(d[27]),"+f"(d[28]),"+f"(d[29]),"+f"(d[30]),"+f"(d[31]),"+f"(d[32]),"+f"(d[33]),"+f"(d[34]),"+f"(d[35]),"+f"(d[36]),"+f"(d[37]),"+f"(d[38]),"+f"(d[39]),"+f"(d[40]),"+f"(d[41]),"+f"(d[42]),"+f"(d[43]),"+f"(d[44]),"+f"(d[45]),"+f"(d[46]),"+f"(d[47]),"+f"(d[48]),"+f"(d[49]),"+f"(d[50]),"+f"(d[51]),"+f"(d[52]),"+f"(d[53]),"+f"(d[54]),"+f"(d[55]),"+f"(d[56]),"+f"(d[57]),"+f"(d[58]),"+f"(d[59]),"+f"(d[60]),"+f"(d[61]),"+f"(d[62]),"+f"(d[63]),"+f"(d[64]),"+f"(d[65]),"+f"(d[66]),"+f"(d[67]),"+f"(d[68]),"+f"(d[69]),"+f"(d[70]),"+f"(d[71]),"+f"(d[72]),"+f"(d[73]),"+f"(d[74]),"+f"(d[75]),"+f"(d[76]),"+f"(d[77]),"+f"(d[78]),"+f"(d[79])
    : "r"(al), "r"(ah), "r"(bl), "r"(bh), "n"(TB));
}
template<int TB> __device__ __forceinline__ void wgmma_ss_144_0(float (&d)[96], uint32_t al, uint32_t ah, uint32_t bl, uint32_t bh) {
  asm volatile("{\n.reg .b64 da, db;\nmov.b64 da, {%72, %73};\nmov.b64 db, {%74, %75};\n"
    "wgmma.mma_async.sync.aligned.m64n144k16.f32.bf16.bf16 {%0,%1,%2,%3,%4,%5,%6,%7,%8,%9,%10,%11,%12,%13,%14,%15,%16,%17,%18,%19,%20,%21,%22,%23,%24,%25,%26,%27,%28,%29,%30,%31,%32,%33,%34,%35,%36,%37,%38,%39,%40,%41,%42,%43,%44,%45,%46,%47,%48,%49,%50,%51,%52,%53,%54,%55,%56,%57,%58,%59,%60,%61,%62,%63,%64,%65,%66,%67,%68,%69,%70,%71}, da, db, 1, 1, 1, 1, %76;\n}\n"
    : "+f"(d[0]),"+f"(d[1]),"+f"(d[2]),"+f"(d[3]),"+f"(d[4]),"+f"(d[5]),"+f"(d[6]),"+f"(d[7]),"+f"(d[8]),"+f"(d[9]),"+f"(d[10]),"+f"(d[11]),"+f"(d[12]),"+f"(d[13]),"+f"(d[14]),"+f"(d[15]),"+f"(d[16]),"+f"(d[17]),"+f"(d[18]),"+f"(d[19]),"+f"(d[20]),"+f"(d[21]),"+f"(d[22]),"+f"(d[23]),"+f"(d[24]),"+f"(d[25]),"+f"(d[26]),"+f"(d[27]),"+f"(d[28]),"+f"(d[29]),"+f"(d[30]),"+f"(d[31]),"+f"(d[32]),"+f"(d[33]),"+f"(d[34]),"+f"(d[35]),"+f"(d[36]),"+f"(d[37]),"+f"(d[38]),"+f"(d[39]),"+f"(d[40]),"+f"(d[41]),"+f"(d[42]),"+f"(d[43]),"+f"(d[44]),"+f"(d[45]),"+f"(d[46]),"+f"(d[47]),"+f"(d[48]),"+f"(d[49]),"+f"(d[50]),"+f"(d[51]),"+f"(d[52]),"+f"(d[53]),"+f"(d[54]),"+f"(d[55]),"+f"(d[56]),"+f"(d[57]),"+f"(d[58]),"+f"(d[59]),"+f"(d[60]),"+f"(d[61]),"+f"(d[62]),"+f"(d[63]),"+f"(d[64]),"+f"(d[65]),"+f"(d[66]),"+f"(d[67]),"+f"(d[68]),"+f"(d[69]),"+f"(d[70]),"+f"(d[71])
    : "r"(al), "r"(ah), "r"(bl), "r"(bh), "n"(TB));
}
template<int TB> __device__ __forceinline__ void wgmma_ss_96_0(float (&d)[96], uint32_t al, uint32_t ah, uint32_t bl, uint32_t bh) {
  asm volatile("{\n.reg .b64 da, db;\nmov.b64 da, {%48, %49};\nmov.b64 db, {%50, %51};\n"
    "wgmma.mma_async.sync.aligned.m64n96k16.f32.bf16.bf16 {%0,%1,%2,%3,%4,%5,%6,%7,%8,%9,%10,%11,%12,%13,%14,%15,%16,%17,%18,%19,%20,%21,%22,%23,%24,%25,%26,%27,%28,%29,%30,%31,%32,%33,%34,%35,%36,%37,%38,%39,%40,%41,%42,%43,%44,%45,%46,%47}, da, db, 1, 1, 1, 1, %52;\n}\n"
    : "+f"(d[0]),"+f"(d[1]),"+f"(d[2]),"+f"(d[3]),"+f"(d[4]),"+f"(d[5]),"+f"(d[6]),"+f"(d[7]),"+f"(d[8]),"+f"(d[9]),"+f"(d[10]),"+f"(d[11]),"+f"(d[12]),"+f"(d[13]),"+f"(d[14]),"+f"(d[15]),"+f"(d[16]),"+f"(d[17]),"+f"(d[18]),"+f"(d[19]),"+f"(d[20]),"+f"(d[21]),"+f"(d[22]),"+f"(d[23]),"+f"(d[24]),"+f"(d[25]),"+f"(d[26]),"+f"(d[27]),"+f"(d[28]),"+f"(d[29]),"+f"(d[30]),"+f"(d[31]),"+f"(d[32]),"+f"(d[33]),"+f"(d[34]),"+f"(d[35]),"+f"(d[36]),"+f"(d[37]),"+f"(d[38]),"+f"(d[39]),"+f"(d[40]),"+f"(d[41]),"+f"(d[42]),"+f"(d[43]),"+f"(d[44]),"+f"(d[45]),"+f"(d[46]),"+f"(d[47])
    : "r"(al), "r"(ah), "r"(bl), "r"(bh), "n"(TB));
}
template<int TB> __device__ __forceinline__ void wgmma_ss_96_48(float (&d)[96], uint32_t al, uint32_t ah, uint32_t bl, uint32_t bh) {
  asm volatile("{\n.reg .b64 da, db;\nmov.b64 da, {%48, %49};\nmov.b64 db, {%50, %51};\n"
    "wgmma.mma_async.sync.aligned.m64n96k16.f32.bf16.bf16 {%0,%1,%2,%3,%4,%5,%6,%7,%8,%9,%10,%11,%12,%13,%14,%15,%16,%17,%18,%19,%20,%21,%22,%23,%24,%25,%26,%27,%28,%29,%30,%31,%32,%33,%34,%35,%36,%37,%38,%39,%40,%41,%42,%43,%44,%45,%46,%47}, da, db, 1, 1, 1, 1, %52;\n}\n"
    : "+f"(d[48]),"+f"(d[49]),"+f"(d[50]),"+f"(d[51]),"+f"(d[52]),"+f"(d[53]),"+f"(d[54]),"+f"(d[55]),"+f"(d[56]),"+f"(d[57]),"+f"(d[58]),"+f"(d[59]),"+f"(d[60]),"+f"(d[61]),"+f"(d[62]),"+f"(d[63]),"+f"(d[64]),"+f"(d[65]),"+f"(d[66]),"+f"(d[67]),"+f"(d[68]),"+f"(d[69]),"+f"(d[70]),"+f"(d[71]),"+f"(d[72]),"+f"(d[73]),"+f"(d[74]),"+f"(d[75]),"+f"(d[76]),"+f"(d[77]),"+f"(d[78]),"+f"(d[79]),"+f"(d[80]),"+f"(d[81]),"+f"(d[82]),"+f"(d[83]),"+f"(d[84]),"+f"(d[85]),"+f"(d[86]),"+f"(d[87]),"+f"(d[88]),"+f"(d[89]),"+f"(d[90]),"+f"(d[91]),"+f"(d[92]),"+f"(d[93]),"+f"(d[94]),"+f"(d[95])
    : "r"(al), "r"(ah), "r"(bl), "r"(bh), "n"(TB));
}
__device__ __forceinline__ void wgmma_rs_72(float (&d)[36], uint32_t a0, uint32_t a1, uint32_t a2, uint32_t a3, uint32_t bl, uint32_t bh, int sd) {
  asm volatile("{\n.reg .pred p;\n.reg .b64 db;\nsetp.ne.b32 p, %42, 0;\nmov.b64 db, {%40, %41};\n"
    "wgmma.mma_async.sync.aligned.m64n72k16.f32.bf16.bf16 {%0,%1,%2,%3,%4,%5,%6,%7,%8,%9,%10,%11,%12,%13,%14,%15,%16,%17,%18,%19,%20,%21,%22,%23,%24,%25,%26,%27,%28,%29,%30,%31,%32,%33,%34,%35}, {%36,%37,%38,%39}, db, p, 1, 1, 1;\n}\n"
    : "+f"(d[0]),"+f"(d[1]),"+f"(d[2]),"+f"(d[3]),"+f"(d[4]),"+f"(d[5]),"+f"(d[6]),"+f"(d[7]),"+f"(d[8]),"+f"(d[9]),"+f"(d[10]),"+f"(d[11]),"+f"(d[12]),"+f"(d[13]),"+f"(d[14]),"+f"(d[15]),"+f"(d[16]),"+f"(d[17]),"+f"(d[18]),"+f"(d[19]),"+f"(d[20]),"+f"(d[21]),"+f"(d[22]),"+f"(d[23]),"+f"(d[24]),"+f"(d[25]),"+f"(d[26]),"+f"(d[27]),"+f"(d[28]),"+f"(d[29]),"+f"(d[30]),"+f"(d[31]),"+f"(d[32]),"+f"(d[33]),"+f"(d[34]),"+f"(d[35])
    : "r"(a0), "r"(a1), "r"(a2), "r"(a3), "r"(bl), "r"(bh), "r"(sd));
}
__device__ __forceinline__ void wgmma_rs_48(float (&d)[24], uint32_t a0, uint32_t a1, uint32_t a2, uint32_t a3, uint32_t bl, uint32_t bh, int sd) {
  asm volatile("{\n.reg .pred p;\n.reg .b64 db;\nsetp.ne.b32 p, %30, 0;\nmov.b64 db, {%28, %29};\n"
    "wgmma.mma_async.sync.aligned.m64n48k16.f32.bf16.bf16 {%0,%1,%2,%3,%4,%5,%6,%7,%8,%9,%10,%11,%12,%13,%14,%15,%16,%17,%18,%19,%20,%21,%22,%23}, {%24,%25,%26,%27}, db, p, 1, 1, 1;\n}\n"
    : "+f"(d[0]),"+f"(d[1]),"+f"(d[2]),"+f"(d[3]),"+f"(d[4]),"+f"(d[5]),"+f"(d[6]),"+f"(d[7]),"+f"(d[8]),"+f"(d[9]),"+f"(d[10]),"+f"(d[11]),"+f"(d[12]),"+f"(d[13]),"+f"(d[14]),"+f"(d[15]),"+f"(d[16]),"+f"(d[17]),"+f"(d[18]),"+f"(d[19]),"+f"(d[20]),"+f"(d[21]),"+f"(d[22]),"+f"(d[23])
    : "r"(a0), "r"(a1), "r"(a2), "r"(a3), "r"(bl), "r"(bh), "r"(sd));
}
template<int N,int OFF,int TB> __device__ __forceinline__ void wgmma_ss(float (&d)[96], uint32_t al, uint32_t ah, uint32_t bl, uint32_t bh) {
  if constexpr (N==160 && OFF==0) wgmma_ss_160_0<TB>(d, al, ah, bl, bh);
  else if constexpr (N==144 && OFF==0) wgmma_ss_144_0<TB>(d, al, ah, bl, bh);
  else if constexpr (N==96 && OFF==0) wgmma_ss_96_0<TB>(d, al, ah, bl, bh);
  else if constexpr (N==96 && OFF==48) wgmma_ss_96_48<TB>(d, al, ah, bl, bh);
}

__device__ __forceinline__ void dft3(float2& a, float2& b, float2& c) {
  const float s = 0.86602540378443864676f;
  float2 t = make_float2(b.x + c.x, b.y + c.y), d = make_float2(b.x - c.x, b.y - c.y);
  float2 m = make_float2(fmaf(-0.5f, t.x, a.x), fmaf(-0.5f, t.y, a.y));
  a = make_float2(a.x + t.x, a.y + t.y);
  b = make_float2(fmaf(s, d.y, m.x), fmaf(-s, d.x, m.y));
  c = make_float2(fmaf(-s, d.y, m.x), fmaf(s, d.x, m.y));
}
__device__ __forceinline__ void dft9(float2 (&x)[9]) {
  const float2 w1 = make_float2(0.76604444311897803520f, -0.64278760968653932632f);
  const float2 w2 = make_float2(0.17364817766693034885f, -0.98480775301220805937f);
  const float2 w4 = make_float2(-0.93969262078590838405f, -0.34202014332566873304f);
  dft3(x[0], x[3], x[6]); dft3(x[1], x[4], x[7]); dft3(x[2], x[5], x[8]);
  x[4] = cmul(x[4], w1); x[7] = cmul(x[7], w2); x[5] = cmul(x[5], w2); x[8] = cmul(x[8], w4);
  dft3(x[0], x[1], x[2]); dft3(x[3], x[4], x[5]); dft3(x[6], x[7], x[8]);
  float2 t;
  t = x[1]; x[1] = x[3]; x[3] = t;
  t = x[2]; x[2] = x[6]; x[6] = t;
  t = x[5]; x[5] = x[7]; x[7] = t;
}

__device__ __forceinline__ uint32_t* mod_ptr(Scratch* sc, int u, int t128) {
  const int i = t128 & 15;
  return u < 72 ? sc->moda + (t128 >> 4) * (2 * D_) + 16 * u + 2 * (i & 7) + (i >> 3) : sc->mod + 16 * (u - 72) + i;
}
__device__ __forceinline__ void mod_unit(Scratch* sc, int u, int t128, uint32_t sw_, uint32_t bar, int ph, uint32_t rb, uint32_t tag) {
  const int w = t128 >> 5, l = t128 & 31;
  uint32_t b[18];
#pragma unroll
  for (int i = 0; i < 18; i++) b[i] = lds(red + 512 + (72 * w + 4 * i + (l & 3)) * 4);
  const uint32_t sa = pin(sw_ + (144 * w + (l & 7) + 8 * (l >> 4)) * 32 + (((l >> 3) ^ (l >> 2)) & 1) * 16);
  const uint32_t sr = pin(rb + (l >> 2) * 16 + w * 4);
  uint32_t* const dst = pin(mod_ptr(sc, u, t128));
  const int kind = u / 36;
  const float mul = __uint_as_float(pin(__float_as_uint(kind == 0 ? 16.0f : 1.0f))), add = __uint_as_float(pin(__float_as_uint(kind == 1 || kind == 4 ? 1.0f : 0.0f)));
  mbar_wait(bar, ph);
  if (t128 == 0 && u < 72) TS(10);
  float d[3][4];
#pragma unroll
  for (int i = 0; i < 9; i++) {
    uint32_t a0, a1, a2, a3;
    asm volatile("ldmatrix.sync.aligned.m8n8.x4.trans.shared.b16 {%0,%1,%2,%3}, [%4];" : "=r"(a0), "=r"(a1), "=r"(a2), "=r"(a3) : "r"(sa + i * 512) : "memory");
    if (i < 3) mma16<false>(d[i], a0, a1, a2, a3, b[2 * i], b[2 * i + 1]);
    else mma16<true>(d[i % 3], a0, a1, a2, a3, b[2 * i], b[2 * i + 1]);
  }
  if ((l & 3) == 0) { sts(sr, __float_as_uint(d[0][0] + d[1][0] + d[2][0])); sts(sr + 128, __float_as_uint(d[0][2] + d[1][2] + d[2][2])); }
  bar_sync(4, 128);
  const uint4 v = lds4(rb + (l & 15) * 16);
  const float m = rbf(fmaf(rbf((__uint_as_float(v.x) + __uint_as_float(v.y)) + (__uint_as_float(v.z) + __uint_as_float(v.w))), mul, add));
  if (u < 72 || t128 < 16) *dst = __float_as_uint(m) | tag;
}

__device__ __forceinline__ float rsq(float x) { float r; asm("rsqrt.approx.ftz.f32 %0, %1;" : "=f"(r) : "f"(x)); return r; }
__device__ __forceinline__ void ln_stats2(const float (&a)[18], const float (&b)[18], float sc, float& oa, float& ra, float& ob, float& rb) {
  float v[4] = {0.f, 0.f, 0.f, 0.f}, w[4] = {0.f, 0.f, 0.f, 0.f};
#pragma unroll
  for (int i = 0; i < 18; i += 2) {
    v[0] += a[i]; v[1] = fmaf(a[i], a[i], v[1]); v[2] += b[i]; v[3] = fmaf(b[i], b[i], v[3]);
    w[0] += a[i + 1]; w[1] = fmaf(a[i + 1], a[i + 1], w[1]); w[2] += b[i + 1]; w[3] = fmaf(b[i + 1], b[i + 1], w[3]);
  }
#pragma unroll
  for (int e = 0; e < 4; e++) v[e] += w[e];
#pragma unroll
  for (int o = 16; o; o >>= 1) {
#pragma unroll
    for (int e = 0; e < 4; e++) v[e] += __shfl_xor_sync(0xffffffffu, v[e], o);
  }
  const float ma = v[0] * (1.0f / D_), mb = v[2] * (1.0f / D_);
  ra = sc * rsq(fmaxf(fmaf(-ma, ma, v[1] * (1.0f / D_)), 0.f) + 1e-5f);
  rb = sc * rsq(fmaxf(fmaf(-mb, mb, v[3] * (1.0f / D_)), 0.f) + 1e-5f);
  oa = -ma * ra; ob = -mb * rb;
}

__device__ __forceinline__ float tmat(int c, int q, int j) {
  const int ph = q == 1 ? 1024 * j : (q >> 1) * (c + 128 * j) + 512 * (q & 1);
  return __cosf((float)(((ph + 1024) & 2047) - 1024) * (6.283185307179586f / 2048.0f));
}
__device__ __forceinline__ uint32_t line_off(int k1, int kap, int pi, int f) {
  int kd = 64 * k1 + 9 * kap;
  if (kap == 0 && k1 > 4) kd -= 288;
  if (kd >= D_) kd -= D_;
  return pi * 2400 + ((min(kd, D_ - kd) ^ f) << 3);
}

constexpr int JSK = 5;
struct Ring { uint32_t st, ph; };
template <bool G2, class T> __device__ __forceinline__ void ring_next(T& st, T& ph) {
  if (++st == NST) st = 0;
  ph ^= ((G2 ? 0xDu : 0x1u) >> st) & 1;
}
__device__ __forceinline__ void arrive_if(uint32_t a, uint32_t p) {
  asm volatile("{\n.reg .pred p;\nsetp.ne.u32 p, %1, 0;\n@p mbarrier.arrive.shared::cta.b64 _, [%0];\n}" ::"r"(a), "r"(p) : "memory");
}
template <int NA> __device__ __forceinline__ void reg_fence_n(float (&d)[96]) {
#pragma unroll
  for (int i = 0; i < NA; i++) asm volatile("" : "+f"(d[i])::"memory");
}
template <int MODE>
__device__ __forceinline__ void gemm_main(float (&acc)[96], uint32_t da0, uint32_t da1, uint32_t db0, int wg, Ring& rg,
                                          uint32_t* x1p, const uint32_t (&xr)[18]) {
  static_assert(JSK == NST - 1, "the held slot is the first one that is not refilled by GEMM1");
  constexpr int NKB = MODE == 3 ? 36 : 32, J = MODE == 3 ? J2 : JSK;
  constexpr uint32_t HA = 0x40000040u, HB = MODE == 3 ? 0x40000040u : 0x80000020u;
  constexpr uint32_t KA = 2048 >> 4, KB = MODE == 3 ? (32 >> 4) : (1024 >> 4);
  constexpr int NA = MODE == 3 ? 72 : MODE == 1 ? 96 : 80;
  const uint32_t t = threadIdx.x & 127;
  const uint32_t eb = full0 + 8 * NST;
  uint32_t pb = 0, rel = t == 0, prel = 0, ok = 0;
  int n = MODE == 3 ? NKB - J : X1K + 2 * wg;
#pragma unroll 1
  for (int pass = MODE == 3 ? 0 : -1;; pass++) {
#pragma unroll 1
    do {
      const uint32_t so = rg.st * ((MODE == 3 ? STAGE2 : STAGE) >> 4), cb = eb + 8 * rg.st;
      if (__builtin_expect(!ok, 0)) mbar_wait(full0 + 8 * rg.st, rg.ph);
      reg_fence_n<NA>(acc);
      if (MODE == 1 && wg) {
        wg_fence();
#pragma unroll
        for (int k = 0; k < 4; k++) wgmma_ss<96, 48, 1>(acc, da1 + so + k * KA, HA, db0 + so + k * KB, HB);
        wg_commit();
      }
      wg_fence();
#pragma unroll
      for (int k = 0; k < 4; k++) {
        if (k == 3) { ring_next<MODE == 3>(rg.st, rg.ph); ok = PEEK ? mbar_test(full0 + 8 * rg.st, rg.ph) : 0; }
        if (MODE == 0) wgmma_ss<160, 0, 1>(acc, da0 + so + k * KA, HA, db0 + so + k * KB, HB);
        else if (MODE == 3) wgmma_ss<144, 0, 0>(acc, da0 + so + k * KA, HA, db0 + so + k * KB, HB);
        else wgmma_ss<96, 0, 1>(acc, da0 + so + k * KA, HA, db0 + so + k * KB, HB);
      }
      wg_commit();
      wg_wait<1>();
      reg_fence_n<NA>(acc);
      arrive_if(pb, prel);
      pb = cb; prel = rel;
    } while (--n);
    if (pass == 2 - wg) break;
    if (MODE != 3 && pass < 0) {
      if (blockIdx.x < 128) {
#pragma unroll
        for (int i = 0; i < 9; i++) { x1p[32 * i] = xr[i]; x1p[128 * 288 + 32 * i] = xr[9 + i]; }
      }
      n = NKB - JSK - X1K - 2 * wg;
      continue;
    }
    n = 1;
    if (pass == 0) {
      if (MODE != 3) prel = rel & wg;
      else { rel = 0; if (J < NST) prel = 0; }
      n = J - 1 + wg;
      if (!wg) continue;
      wg_wait<0>();
      arrive_if(pb, prel);
      prel = 0;
    }
    bar_sync(1, 256);
  }
  wg_wait<0>();
  reg_fence_n<NA>(acc);
  if (MODE != 3) arrive_if(pb, MODE == 1 ? prel & ~wg : prel);
}

constexpr float GK1 = 2.0f * 0.7978845608028654f, GK3 = 8.0f * 0.044715f * 0.7978845608028654f;

__device__ __forceinline__ int kb2_order(int i) { const int wv = i / 6; return 6 * (i - 6 * wv) + ((0x431250 >> (4 * wv)) & 7); }

__device__ __forceinline__ void wait_flags(const unsigned* base, int n, int idx, unsigned target, uint64_t& ready) {
  if ((ready >> idx) & 1) return;
  const int l = threadIdx.x & 31;
  int it = 0;
  while (true) {
    unsigned a = ld_rlx(base + l), b = l + 32 < n ? ld_rlx(base + l + 32) : target;
    ready = (uint64_t)__ballot_sync(0xffffffffu, (int)(a - target) >= 0) | ((uint64_t)__ballot_sync(0xffffffffu, (int)(b - target) >= 0) << 32);
    if (((ready >> idx) & 1) || ++it > SPIN_MAX) break;
  }
}

enum { B_FULL = 0, B_EMPTY = 6, B_S4 = 12, B_S5, B_LAND, B_FLT = B_LAND + 6, B_Z1, B_Z2, B_GO, B_X, B_WM, B_NUM, B_W0 = B_NUM };

__global__ void __launch_bounds__(NTHR, 1)
fused_kernel(const Params p, const __grid_constant__ Maps maps) {
  extern __shared__ __align__(1024) uint8_t smem_raw[];
  const int tid = threadIdx.x, cta = blockIdx.x, t128 = tid & 127;
  const int wp = __shfl_sync(0xffffffffu, tid >> 5, 0), wg = wp >> 2;
  const int l = tid & 31, g = l >> 2, t = l & 3;
  Scratch* const sc = p.s;
  const bool rows = cta < 128;
  const int R = cta - 12;

  uint32_t xr[18];
  uint32_t cv[3];
  const unsigned ep = ld_rlx(&sc->cnt[C_EP]) + 1;
  if (tid == 0) TS(0);
  if (wg == 2) {
#pragma unroll
    for (int i = 0; i < 3; i++) cv[i] = ld_nc(reinterpret_cast<const uint32_t*>(p.c) + min(t128 + 128 * i, 287));
    if (wp == 9 && l < 9 && rows) {
      const int h = 9 * cta + l;
      prefetch_l2(reinterpret_cast<const uint8_t*>(p.wmod) + (size_t)(h >> 1) * (12 * D_) + (h & 1) * (2 * D_), 2 * D_);
    }
    if (tid == 256 && cta < 72) {
      mbar_init(full0 + 8 * B_W0, 1);
      fence_async_smem();
      mbar_expect(full0 + 8 * B_W0, 18432);
#pragma unroll 1
      for (int i = 0; i < 3; i++) tma2d(sbase + O_P2 + i * 6144, &maps.wm, 16 * cta, 192 * i, full0 + 8 * B_W0);
    }
    __syncwarp();
#pragma unroll 1
    for (int u = cta < 72 ? cta : 72 + cta; u < 216; u += u < 72 ? 72 : NCTA) if (u < 72 || t128 < 16) *mod_ptr(sc, u, t128) = 0;
    if (wp == 11 && smem_u32(smem_raw) != sbase) __trap();
    if (wp >= 10 && elect()) {
#pragma unroll 1
      for (int i = wp - 10; i < B_NUM; i += 2) mbar_init(full0 + 8 * i, i == B_FLT ? 4 : i == B_WM ? 3 : i < B_LAND ? 2 : 1);
      fence_async_smem();
    }
    __syncwarp();
  }
  CK(0);
  auto load_x = [&]() {
    const uint32_t* xs = reinterpret_cast<const uint32_t*>(p.x) + (size_t)(cta + 256 * wp) * 288 + l;
#pragma unroll
    for (int i = 0; i < 9; i++) { xr[i] = ld_nc(xs + 32 * i); xr[9 + i] = ld_nc(xs + 128 * 288 + 32 * i); }
  };
  if (rows && wg < 2) load_x();
  if (tid == 64 && cta == NCTA - 1) prefetch_l2(p.tab, sizeof(T_TAB));
  __syncwarp();
  const uint32_t tag16 = (ep & 0x7fffu) | 0x8000u, tag1 = ep & 1u;

  if (wg == 2) {
#pragma unroll
    for (int i = 0; i < 3; i++) {
      const float c0 = bf_lo(cv[i]), c1 = bf_hi(cv[i]);
      sts(red + 512 + min(t128 + 128 * i, 287) * 4, pack_bf16(__fdividef(c0, 1.0f + __expf(-c0)), __fdividef(c1, 1.0f + __expf(-c1))));
    }
    if (wp == 9 && l < 12) asm volatile("prefetch.tensormap [%0];" ::"l"(&maps.z1 + l) : "memory");
    bar_sync(4, 128);
    if (cta < 72) {
      mod_unit(sc, cta, t128, sbase + O_P2, full0 + 8 * B_W0, 0, red, tag16);
      if (t128 == 0) TS(25);
    }
    CK(1);
  }
  const int pi = R / 15, col0 = 20 * (R - 15 * pi);
  const int xu = DF_ * pi + col0, xv = DF_ * (pi ? 16 - pi : 8) + col0;
  auto load_filter = [&](int a) {
    const int x = (a & 1) ? xv : xu;
    const bool wide = (x & 15) > 12;
    mbar_expect(full0 + 8 * B_FLT, wide ? 12288 : 8192);
    tma2d(sbase + O_RAW + a * 12288, &maps.wf[a & 2], x & ~15, 0, full0 + 8 * B_FLT);
    if (wide) tma2d(sbase + O_RAW + a * 12288 + 8192, &maps.wf[(a & 2) + 1], (x & ~15) + 32, 0, full0 + 8 * B_FLT);
  };
  const int kap = 8 * ((wp & 3) ^ (wg & 1)) + g;
  uint4 af[4];
  if (rows) {
    uint32_t tb[4];
#pragma unroll
    for (int i = 0; i < 4; i++) tb[i] = pack_bf16(tmat(cta, 8 * (i >> 1) + g, 2 * t + 8 * (i & 1)), tmat(cta, 8 * (i >> 1) + g, 2 * t + 8 * (i & 1) + 1));
    uint32_t sb1[3], lo[9];
#pragma unroll
    for (int i = 0; i < 4; i++) tb[i] = pin(tb[i]);
#pragma unroll
    for (int i = 0; i < 3; i++) {
      const int d = 48 * wp + 16 * i + (l & 15);
      sb1[i] = pin(sbase + O_B1 + (l >> 4) * 9216 + (d % 9) * 1024 + (d & 63) * 16);
    }
    const uint32_t snt = pin(sbase + O_NRM + ((l & 7) + 8 * (l >> 4)) * 1168 + (48 * wp + (l & 8)) * 2);
    uint2 ms[3], mc[3];
    const uint32_t smask = pin(t ? 0u : 0xffff0000u);
    const uint32_t* const mp = pin(sc->moda + (cta >> 4) * (2 * D_) + 48 * wp + 2 * g);
    auto load_mod = [&]() {
#pragma unroll
      for (int i = 0; i < 3; i++) { ms[i] = ld_rlx2(mp + 16 * i); mc[i] = ld_rlx2(mp + D_ + 16 * i); }
    };
    if (wg < 2) {
#pragma unroll
      for (int k1 = 0; k1 < 9; k1++) lo[k1] = pin(sbase + O_Z1 + line_off(k1, kap, 4 * wg + t, cta & 3));
      float a[18], b[18];
#pragma unroll
      for (int i = 0; i < 9; i++) { a[2 * i] = bf_lo(xr[i]); a[2 * i + 1] = bf_hi(xr[i]); b[2 * i] = bf_lo(xr[9 + i]); b[2 * i + 1] = bf_hi(xr[9 + i]); }
      float oa, ra, ob, rb;
      ln_stats2(a, b, 1.0f, oa, ra, ob, rb);
      CK(1);
      const uint32_t sn = sbase + O_NRM + wp * 2336 + l * 4;
#pragma unroll
      for (int i = 0; i < 9; i++) {
        sts(sn + i * 128, pack_bf16(fmaf(a[2 * i], ra, oa), fmaf(a[2 * i + 1], ra, oa)));
        sts(sn + 1168 + i * 128, pack_bf16(fmaf(b[2 * i], rb, ob), fmaf(b[2 * i + 1], rb, ob)));
      }
      CK(2);
      bar_arrive(10, NTHR);
      load_mod();
#pragma unroll
      for (int kk = 0; kk < 4; kk++) af[kk] = ld_nc4(p.tab + TB_F + kk * 128 + (t128 ^ (wg << 5)));
      bar_sync(1, 256);
      if (tid == 0) TS(2);
    } else {
      bar_sync(10, NTHR);
      load_mod();
      CK(2);
      if (PFF && wp >= 12 - PFF && elect()) prefetch_l2(reinterpret_cast<const uint8_t*>(wp == 10 ? p.wr : p.wi) + cta * 9248, 9248);
      __syncwarp();
    }
    float rs[3][8];
#pragma unroll
    for (int i = 0; i < 3; i++) {
      uint32_t a0, a1, a2, a3;
      asm volatile("ldmatrix.sync.aligned.m8n8.x4.trans.shared.b16 {%0,%1,%2,%3}, [%4];" : "=r"(a0), "=r"(a1), "=r"(a2), "=r"(a3)
                   : "r"(snt + 32 * i) : "memory");
      mma16<false>(&rs[i][0], a0, a1, a2, a3, tb[0], tb[1]);
      mma16<false>(&rs[i][4], a0, a1, a2, a3, tb[2], tb[3]);
    }
    CK(3);
    {
      int it = 0;
#pragma unroll 1
      while (true) {
        uint32_t bad = 0;
#pragma unroll
        for (int i = 0; i < 3; i++) bad |= diff2(ms[i].x, ms[i].y, tag16) | diff2(mc[i].x, mc[i].y, tag16);
        if (!any(bad & 0xffffu) || ++it > SPIN_MAX) break;
        load_mod();
      }
      CK(4);
      if (tid == 0) TS(3);
#pragma unroll
      for (int i = 0; i < 3; i++) {
        const float c0 = bf_hi(mc[i].x), c1 = bf_hi(mc[i].y);
        const float s0 = __uint_as_float(ms[i].x & smask), s1 = __uint_as_float(ms[i].y & smask);
        stmatrix4(sb1[i], pack_bf16(fmaf(rs[i][0], c0, s0), rs[i][1] * c0), pack_bf16(fmaf(rs[i][2], c1, s1), rs[i][3] * c1),
                  pack_bf16(rs[i][4] * c0, rs[i][5] * c0), pack_bf16(rs[i][6] * c1, rs[i][7] * c1));
      }
    }
    fence_async_smem();
    CK(5);
    if (wg == 2) {
      bar_arrive(5, NTHR);
      if (R >= 0 && elect()) load_filter(wp - 8);
      __syncwarp();
    } else {
      bar_sync(5, NTHR);
      CK(6);
      float acc[36];
      const uint32_t db = (((sbase + O_B1 + wg * 9216) & 0x3FFFF) >> 4) | ((128 >> 4) << 16);
      wg_fence();
#pragma unroll
      for (int kk = 0; kk < 4; kk++) wgmma_rs_72(acc, af[kk].x, af[kk].y, af[kk].z, af[kk].w, db + kk * 16, 1024 >> 4, kk);
      wg_commit();
      wg_wait<0>();
      reg_fence(acc);
      CK(7);
      float2 za[9], zb[9];
#pragma unroll
      for (int i = 0; i < 9; i++) { za[i] = make_float2(acc[4 * i], acc[4 * i + 2]); zb[i] = make_float2(acc[4 * i + 1], acc[4 * i + 3]); }
      dft9(za); dft9(zb);
      if (kap == 0) {
#pragma unroll
        for (int k = 1; k < 5; k++) {
          float2 a = za[k], b = za[9 - k];
          za[k] = make_float2(a.x + b.x, a.y - b.y); za[9 - k] = make_float2(a.y + b.y, b.x - a.x);
          a = zb[k]; b = zb[9 - k];
          zb[k] = make_float2(a.x + b.x, a.y - b.y); zb[9 - k] = make_float2(a.y + b.y, b.x - a.x);
        }
        sts2(lo[0] + 288 * 8, set_tag(pack_bf16(za[0].y, 0.f), tag1), pack_bf16(zb[0].y, 0.f));
        za[0].y = 0.f; zb[0].y = 0.f;
      }
      __syncwarp();
#pragma unroll
      for (int k1 = 0; k1 < 9; k1++) sts2(lo[k1], set_tag(pack_bf16(za[k1].x, za[k1].y), tag1), pack_bf16(zb[k1].x, zb[k1].y));
      fence_async_smem();
      CK(8);
      bar_arrive(2 + wg, 160);
      {
        const uint32_t fx = (((cta >> 4) ^ cta) & 3) << 3, dl = O_IN - O_Z1, st = sbase + O_ST + 15360 + tid * 16;
        sts4(st, (lo[0] ^ fx) + dl, (lo[1] ^ fx) + dl, (lo[2] ^ fx) + dl, (lo[3] ^ fx) + dl);
        sts4(st + 4096, (lo[4] ^ fx) + dl, (lo[5] ^ fx) + dl, (lo[6] ^ fx) + dl, (lo[7] ^ fx) + dl);
        sts4(st + 8192, (lo[8] ^ fx) + dl, (lo[0] ^ fx) + dl + (kap ? 0 : 288 * 8),
             sbase + O_B3 + wg * 1024 + (l >> 4) * 2048 + (2 * (kap & 24) + (l & 15)) * 16, 0);
      }
    }
    {
      uint32_t sy[6];
#pragma unroll
      for (int i = 0; i < 6; i++) {
        const int rr = 16 * (wp & 3) + g + 8 * (i & 1);
        sy[i] = sbase + O_Y + (t * 584 + 64 * ((3 * wg + (i >> 1) + 63 - rr) % 9) + rr) * 4;
      }
      sts4(sbase + O_ST + tid * 16, movm(tb[0]), movm(tb[2]), movm(tb[1]), movm(tb[3]));
      sts4(sbase + O_ST + 6144 + tid * 16, sy[0], sy[1], sy[2], sy[3]);
      sts2(sbase + O_ST + 12288 + tid * 8, sy[4], sy[5]);
    }
  } else {
    __syncthreads();
  }

  if ((wp >> 1) == 4) {
    if (rows) {
      const int slot = 4 * (cta & 7) + ((cta >> 4) & 3) + 32 * (2 * (cta >> 6) + ((cta >> 3) & 1));
      const uint32_t c0 = upin(40 * slot), c1 = upin(60 * (wp - 8)), src = upin(sbase + O_Z1 + (wp - 8) * 9600);
      const CUtensorMap* mp = upin(&maps.z1);
      unsigned* hint = pin(&sc->cnt[C_Z1 + 32 * (wp - 8)]);
      bar_sync(wp - 6, 160);
      if (elect()) {
        tma_st2d(mp, src, c0, c1);
        HW();
        red_add(hint, 1);
        if (wp == 8) TS(4);
      }
    } else {
      int it = 0;
      while (any((ld_rlx(sc->moda + 36 * l) ^ tag16) & 0xffffu) && ++it < SPIN_MAX) {}
      if (elect()) { load_filter(wp - 8); load_filter(wp - 6); }
    }
    __syncwarp();
  }
  auto load_wm = [&](int u) {
    if (wp > 8 && elect()) {
      mbar_expect(full0 + 8 * B_WM, 6144);
      tma2d(sbase + O_NRM + (wp - 9) * 6144, &maps.wm, 16 * u, 192 * (wp - 9), full0 + 8 * B_WM);
    }
    __syncwarp();
  };
  if (R >= 0) {
    const int nl = (col0 + wp < DF_) + (wg < 2 && col0 + wp + 12 < DF_);
    uint4 cf[2][4], G[4];
#pragma unroll
    for (int i = 0; i < 4; i++) {
      cf[0][i] = __ldg(p.tab + TB_P2 + i * 32 + l);
      cf[1][i] = __ldg(p.tab + TB_P2 + (pi ? i : 4 + i) * 32 + l);
      G[i] = __ldg(p.tab + TB_P2 + (8 + i) * 32 + l);
    }
    const uint32_t* zin = sc->z1 + (size_t)R * 5120;
    if (wp == 10) {
      const uint32_t* zu = upin(zin);
      if (elect()) mbar_expect(full0 + 8 * B_Z1, 20480);
      wait_cnt(&sc->cnt[C_Z1 + 32 * (pi >> 2)], 128 * ep);
      if (elect()) {
        bulk_ld(sbase + O_P2, zu, 20480, full0 + 8 * B_Z1);
        TS(12);
      }
      __syncwarp();
    }
    mbar_wait(full0 + 8 * B_FLT, 0);
    CK(9);
    float wn[16], wc[16];
#pragma unroll 1
    for (int ln = nl - 1; ln >= 0; ln--) {
      const int col = col0 + wp + 12 * ln, k2 = (57 * col) & 63;
      const bool cj = k2 > 32 || (k2 == 32 && col != 288);
      const float nr = ((col & 31) == 0 && col != 0 && col != 288 ? 0.5f : 1.0f) / ((float)S_ * D_), ni = cj ? -nr : nr;
#pragma unroll
      for (int i = 0; i < 16; i++) wn[i] = wc[i];
#pragma unroll
      for (int cl = 0; cl < 2; cl++) {
        const int v = cl ^ (cj && pi), e = ((v ? xv : xu) & 15) + wp + 12 * ln, sh = e < 32 ? 6 : 5;
        const uint32_t base = sbase + O_RAW + v * 12288 + (e < 32 ? 2 * e : 8192 - 64 + 2 * e), msk = e < 32 ? 0x30 : 0x10;
        const int dm = v ? (cj || pi ? -1 : 0) : 0;
#pragma unroll
        for (int tt = 0; tt < 4; tt++) {
          const int kc = g + 64 * (tt >> 1) + 16 * t + 8 * (tt & 1);
          uint32_t a = base + ((((cj ? -kc : kc) + dm) & 127) << sh);
          a ^= (a >> 3) & msk;
          wc[4 * tt + 2 * cl] = lds_bf(a) * nr; wc[4 * tt + 2 * cl + 1] = lds_bf(a + 24576) * ni;
        }
      }
    }
    const float al = __uint_as_float(pin((pi ? 0x3f800000u : 0u) + (l >> 5)));
    const uint32_t tagv = pin(tag1 + (l >> 5));
    CK(10);
    uint32_t off = pin(l * 160 + ((wp ^ (g & 3)) << 3));
    uint32_t offo = pin(sbase + O_P2 + 20480 + off - 64 * l), po = 3072;
    unsigned* hz2 = pin(&sc->cnt[C_Z2]);
    const uint32_t do2 = pin(12288 - 32 * l);
    const CUtensorMap* mz2 = upin(&maps.z2[wp == 0]);
    const uint32_t sz2 = upin(sbase + O_P2 + 20480 + (wp ? 0 : 12288)), cz2 = upin(40 * R + (wp ? 0 : 24));
    mbar_wait(full0 + 8 * B_Z1, 0);
    CK(11);
    if (tid == 0) TS(8);
    if (wg == 2) load_wm(72 + cta);
    uint2 v[4], v2[4];
    const uint32_t o2 = nl > 1 ? 96 : 0;
#pragma unroll
    for (int i = 0; i < 4; i++) { v[i] = lds2(sbase + O_P2 + off + i * 5120); v2[i] = lds2(sbase + O_P2 + off + o2 + i * 5120); }
    auto bad2 = [&]() {
      return any(or3(or3(diff2(v[0].x, v[1].x, tagv), diff2(v[2].x, v[3].x, tagv), diff2(v2[0].x, v2[1].x, tagv)), diff2(v2[2].x, v2[3].x, tagv), 0) & 1);
    };
    if (__builtin_expect(bad2() && nl, 0)) {
      FAILCNT(0);
      int it = 0;
      do {
#pragma unroll
        for (int i = 0; i < 4; i++) {
          v[i] = ld_rlx2(reinterpret_cast<const uint8_t*>(zin) + off + i * 5120);
          v2[i] = ld_rlx2(reinterpret_cast<const uint8_t*>(zin) + off + o2 + i * 5120);
        }
      } while (bad2() && ++it < SPIN_MAX);
    }
#pragma unroll 1
    for (int ln = 0; ln < nl; ln++, offo += do2, po = 2048) {
      float d[4][4];
      uint32_t A[8];
#pragma unroll
      for (int h = 0; h < 2; h++) {
        mma16<false>(d[2 * h], cf[0][0].x, cf[0][0].y, cf[0][0].z, cf[0][0].w, v[h].x, v[2 + h].x);
        mma16<false>(d[2 * h + 1], cf[1][0].x, cf[1][0].y, cf[1][0].z, cf[1][0].w, v[h].y, v[2 + h].y);
      }
      if (ln) { fence_async_smem(); bar_arrive(15, NTHR); }
#pragma unroll
      for (int h = 0; h < 2; h++)
#pragma unroll
        for (int L = 0; L < 2; L++) {
          const uint4 tw = cf[L][2 + h];
          const float* z = d[2 * h + L];
          const float2 z0 = cmul(make_float2(z[0], z[2]), make_float2(__uint_as_float(tw.x), __uint_as_float(tw.y)));
          const float2 z1 = cmul(make_float2(z[1], z[3]), make_float2(__uint_as_float(tw.z), __uint_as_float(tw.w)));
          A[4 * h + L] = pack_bf16(z0.x, z0.y); A[4 * h + 2 + L] = pack_bf16(z1.x, z1.y);
        }
#pragma unroll
      for (int tt = 0; tt < 4; tt++) {
        mma16<false>(d[tt], A[0], A[1], A[2], A[3], G[tt].x, G[tt].y);
        mma16<true>(d[tt], A[4], A[5], A[6], A[7], G[tt].z, G[tt].w);
      }
#pragma unroll
      for (int tt = 0; tt < 4; tt++) {
        const float ar = d[tt][0], aj = d[tt][1], br = d[tt][2], bj = d[tt][3];
        const float2 y1 = cmul(make_float2(fmaf(-al, bj, ar), fmaf(al, br, aj)), make_float2(wc[4 * tt], wc[4 * tt + 1]));
        const float2 y2 = cmul(make_float2(fmaf(al, ar, bj), fmaf(al, aj, -br)), make_float2(wc[4 * tt + 2], wc[4 * tt + 3]));
        A[2 * tt] = pack_bf16(fmaf(al, y2.x, y1.x), fmaf(-al, y2.y, -y1.y));
        A[2 * tt + 1] = pack_bf16(fmaf(al, y1.y, -y2.y), fmaf(al, y1.x, -y2.x));
      }
#pragma unroll
      for (int i = 0; i < 16; i++) wc[i] = wn[i];
#pragma unroll
      for (int i = 0; i < 4; i++) v[i] = v2[i];
#pragma unroll
      for (int tt = 0; tt < 4; tt++) {
        mma16<false>(d[tt], A[0], A[1], A[2], A[3], G[tt].x, G[tt].y);
        mma16<true>(d[tt], A[4], A[5], A[6], A[7], G[tt].z, G[tt].w);
      }
#pragma unroll
      for (int h = 0; h < 2; h++)
#pragma unroll
        for (int L = 0; L < 2; L++) {
          const uint4 tw = cf[L][2 + h];
          const float2 z0 = cmul(make_float2(d[2 * h][2 * L], d[2 * h][2 * L + 1]), make_float2(__uint_as_float(tw.x), __uint_as_float(tw.y)));
          const float2 z1 = cmul(make_float2(d[2 * h + 1][2 * L], d[2 * h + 1][2 * L + 1]), make_float2(__uint_as_float(tw.z), __uint_as_float(tw.w)));
          A[4 * h + 2 * L] = movm(pack_bf16(z0.x, z1.x)); A[4 * h + 2 * L + 1] = movm(pack_bf16(z0.y, z1.y));
        }
#pragma unroll
      for (int h = 0; h < 2; h++) {
        mma16<false>(d[0], cf[0][1].x, cf[0][1].y, cf[0][1].z, cf[0][1].w, A[4 * h], A[4 * h + 1]);
        mma16<false>(d[1], cf[1][1].x, cf[1][1].y, cf[1][1].z, cf[1][1].w, A[4 * h + 2], A[4 * h + 3]);
#pragma unroll
        for (int e = 0; e < 2; e++)
          sts2(offo + (2 * h + e) * po, set_tag(pack_bf16(d[0][e], d[0][2 + e]), tagv), pack_bf16(d[1][e], d[1][2 + e]));
      }
      CK(12 + ln);
    }
    fence_async_smem();
    if (nl < 2 && wp != 8) bar_arrive(15, NTHR);
    if (wp & 7) { if (wg < 2) bar_arrive(6, 256); }
    else {
      if (wp) bar_sync(15, NTHR); else bar_sync(6, 256);
      if (elect()) {
        tma_st2d(mz2, sz2, cz2, 0);
        HW();
        if (wp == 0) { red_add(hz2, 1); TS(9); }
      }
      __syncwarp();
    }
  }
  if (wg == 2) {
#pragma unroll 1
    for (int u = 72 + cta, k = 0; u < 216; u += NCTA, k ^= 1) {
      if (R < 0) { fence_async_smem(); bar_sync(4, 128); load_wm(u); }
      mod_unit(sc, u, t128, sbase + O_NRM, full0 + 8 * B_WM, k, red + 256 - 256 * k, tag16);
    }
    fence_async_smem();
    CK(13);
  }

  const int grp = cta / 11, m1 = cta - 11 * grp;
  const bool helper = (m1 & 3) == 3;
  const int f1 = 384 * grp + (helper ? 192 : 128) * (m1 >> 2);
  const int d1 = 160 * (m1 & 3), flip = m1 >= 7;
  const int a1bytes = helper ? 24576 : 16384;
  auto load_a1 = [&](int st, int kb) {
    mbar_expect(full0 + 8 * st, a1bytes);
    tma4d_ef(sbase + st * STAGE, helper ? &maps.w1b : &maps.w1a, 4 * (kb >> 3), 16 * (kb & 7), f1 >> 6, full0 + 8 * st);
  };

  if (rows) {
#pragma unroll
    for (int kk = 0; kk < 4; kk++) af[kk] = __ldg(p.tab + TB_E + kk * 128 + t128);
    const uint4 c0 = lds4(sbase + O_ST + tid * 16), c1 = lds4(sbase + O_ST + 6144 + tid * 16);
    const uint2 c2 = lds2(sbase + O_ST + 12288 + tid * 8);
    const uint32_t tb[4] = {c0.x, c0.y, c0.z, c0.w}, sy[6] = {c1.x, c1.y, c1.z, c1.w, c2.x, c2.y};
    const uint32_t l8 = pin(8 * l), syl = pin(sbase + O_Y + wp * 2336 + 8 * l);
    uint32_t sh3[3], ham[3], hom[3];
#pragma unroll
    for (int k = 0; k < 3; k++) {
      const int pos = k && (l >> 4) == k - 1 ? (l & 8) + 4 * (l & 1) + ((l >> 1) & 3) : 4 * (l & 3) + ((l >> 2) & 3);
      const int sw = 2 * cta + (wp & 1), ph = pos ^ ((sw & 3) << 2);
      sh3[k] = pin(sbase + O_B3 + (wp >> 1) * 4608 + (l >> 4) * 256 + (wp & 1) * 128 + ph * 4);
      const bool tg = ((ph ^ sw) & 7) == 0;
      ham[k] = pin(tg ? ~1u : ~0u); hom[k] = pin(tg ? tag1 : 0u);
    }
    const int slot = 4 * (cta >> 4) + ((cta >> 1) & 3) + 32 * (2 * ((cta >> 3) & 1) + (cta & 1));
    const uint32_t* zin = sc->z2 + (size_t)slot * 4800;
    if (wg == 2) {
      {
        uint4 v[4];
        const int i3 = min(t128 + 384, 431);
        int it = 0;
        while (true) {
          uint32_t bad = 0;
#pragma unroll
          for (int k = 0; k < 4; k++) v[k] = ld_rlx4(sc->mod + 4 * (k < 3 ? t128 + 128 * k : i3));
#pragma unroll
          for (int k = 0; k < 4; k++) {
            v[k].x ^= tag16; v[k].y ^= tag16; v[k].z ^= tag16; v[k].w ^= tag16;
            bad |= v[k].x | v[k].y | v[k].z | v[k].w;
          }
          if (!any(bad & 0xffffu) || ++it > SPIN_MAX) break;
        }
#pragma unroll
        for (int k = 0; k < 4; k++) sts4(sbase + O_MOD + 16 * (k < 3 ? t128 + 128 * k : i3), v[k].x, v[k].y, v[k].z, v[k].w);
      }
      CK(14);
      bar_sync(10, NTHR);
      mbar_wait(full0 + 8 * B_Z2, 0);
      if (elect()) {
        load_a1(wp - 8, wp - 8);
        if (wp > 8 && wp - 8 < NG1) prefetch_l2(reinterpret_cast<const uint8_t*>(p.w1) + (size_t)(128 * (4 * ((wp - 8) >> 1) + (cta >> 5)) + 64 * (wp & 1) + 2 * (cta & 31)) * (2 * F_), 4 * F_);
      }
      __syncwarp();
    } else {
      const uint4 e0 = lds4(sbase + O_ST + 15360 + tid * 16), e1 = lds4(sbase + O_ST + 19456 + tid * 16), e2 = lds4(sbase + O_ST + 23552 + tid * 16);
      const uint32_t lo[9] = {e0.x, e0.y, e0.z, e0.w, e1.x, e1.y, e1.z, e1.w, e2.x}, lx = e2.y, sb3 = e2.z;
      bar_arrive(10, NTHR);
      CK(14);
      if (wp == 1) {
        const uint32_t* zu = upin(zin);
        if (elect()) mbar_expect(full0 + 8 * B_Z2, 19200);
        wait_cnt(&sc->cnt[C_Z2], 120 * ep);
        if (elect()) {
          bulk_ld(sbase + O_IN, zu, 19200, full0 + 8 * B_Z2);
          TS(14);
        }
        __syncwarp();
      }
      mbar_wait(full0 + 8 * B_Z2, 0);
      CK(15);
      if (tid == 0) TS(11);
      uint2 v[10];
#pragma unroll
      for (int k1 = 0; k1 < 10; k1++) v[k1] = lds2(k1 < 9 ? lo[k1] : lx);
      auto bad3 = [&]() {
        return any(or3(or3(diff2(v[0].x, v[1].x, tag1), diff2(v[2].x, v[3].x, tag1), diff2(v[4].x, v[5].x, tag1)), diff2(v[6].x, v[7].x, tag1), diff2(v[8].x, v[9].x, tag1)) & 1);
      };
      if (__builtin_expect(bad3(), 0)) {
        FAILCNT(1);
        int it = 0;
        do {
#pragma unroll
          for (int k1 = 0; k1 < 10; k1++) v[k1] = ld_rlx2(reinterpret_cast<const uint8_t*>(zin) + ((k1 < 9 ? lo[k1] : lx) - (sbase + O_IN)));
        } while (bad3() && ++it < SPIN_MAX);
      }
      float2 za[9], zb[9];
#pragma unroll
      for (int i = 0; i < 9; i++) { za[i] = make_float2(bf_lo(v[i].x), bf_hi(v[i].x)); zb[i] = make_float2(bf_lo(v[i].y), bf_hi(v[i].y)); }
      if (kap == 0) {
#pragma unroll
        for (int k = 1; k < 5; k++) {
          float2 a = za[k], b = za[9 - k];
          za[k] = make_float2(a.x - b.y, a.y + b.x); za[9 - k] = make_float2(a.x + b.y, b.x - a.y);
          a = zb[k]; b = zb[9 - k];
          zb[k] = make_float2(a.x - b.y, a.y + b.x); zb[9 - k] = make_float2(a.x + b.y, b.x - a.y);
        }
        za[0].y = bf_lo(v[9].x); zb[0].y = bf_lo(v[9].y);
      }
      __syncwarp();
      dft9(za); dft9(zb);
#pragma unroll
      for (int n = 0; n < 8; n += 2) {
        const int i0 = (9 - n) % 9, i1 = 8 - n;
        stmatrix4(sb3 + n * 2048, pack_bf16(za[i0].x, zb[i0].x), pack_bf16(za[i0].y, zb[i0].y), pack_bf16(za[i1].x, zb[i1].x), pack_bf16(za[i1].y, zb[i1].y));
      }
      stmatrix2(sb3 + 8 * 2048, pack_bf16(za[1].x, zb[1].x), pack_bf16(za[1].y, zb[1].y));
      fence_async_smem();
    }
    CK(16);
    __syncthreads();
    CK(17);
    float acc[24];
    const uint32_t db = (((sbase + O_B3 + wg * 6144) & 0x3FFFF) >> 4) | ((128 >> 4) << 16);
    wg_fence();
#pragma unroll
    for (int kk = 0; kk < 4; kk++) wgmma_rs_48(acc, af[kk].x, af[kk].y, af[kk].z, af[kk].w, db + kk * 16, 1024 >> 4, kk);
    wg_commit();
    uint32_t ga[9];
    uint2 sh[9], sw[9];
    if (wg < 2) {
#pragma unroll
      for (int i = 0; i < 9; i++) {
        const uint2 v = lds2(l8 + sbase + O_MOD + 256 * i);
        ga[i] = __byte_perm(v.x, v.y, 0x7632);
        sh[i] = lds2(l8 + sbase + O_MOD + 4 * D_ + 256 * i);
        sw[i] = lds2(l8 + sbase + O_MOD + 8 * D_ + 256 * i);
      }
    }
    wg_wait<0>();
    reg_fence(acc);
    CK(18);
#pragma unroll
    for (int i = 0; i < 3; i++) {
      const float* a = &acc[8 * i];
      const uint32_t a0 = pack_bf16(a[0], a[1]), a1 = pack_bf16(a[2], a[3]), a2 = pack_bf16(a[4], a[5]), a3 = pack_bf16(a[6], a[7]);
#pragma unroll
      for (int jh = 0; jh < 2; jh++) {
        float y[4];
        mma16<false>(y, a0, a1, a2, a3, tb[2 * jh], tb[2 * jh + 1]);
        sts(sy[2 * i] + jh * (4 * 584 * 4), pack_bf16(y[0], y[1]));
        sts(sy[2 * i + 1] + jh * (4 * 584 * 4), pack_bf16(y[2], y[3]));
      }
    }
    CK(19);
    if (wg == 2) bar_arrive(7, NTHR);
    else {
      bar_sync(7, NTHR);
      CK(20);
      float a[18], b[18];
#pragma unroll
      for (int i = 0; i < 9; i++) {
        const uint2 y = lds2(syl + 256 * i);
        xr[i] = hfma2(ga[i], __byte_perm(y.x, y.y, 0x5410), xr[i]);
        xr[9 + i] = hfma2(ga[i], __byte_perm(y.x, y.y, 0x7632), xr[9 + i]);
        a[2 * i] = bf_lo(xr[i]); a[2 * i + 1] = bf_hi(xr[i]); b[2 * i] = bf_lo(xr[9 + i]); b[2 * i + 1] = bf_hi(xr[9 + i]);
      }
      float oa, ra, ob, rb;
      ln_stats2(a, b, 1.0f, oa, ra, ob, rb);
      CK(21);
#pragma unroll
      for (int i = 0; i < 9; i++) {
        const float c0 = __uint_as_float(sw[i].x), c1 = __uint_as_float(sw[i].y), s0 = __uint_as_float(sh[i].x), s1 = __uint_as_float(sh[i].y);
        a[2 * i] = fmaf(fmaf(a[2 * i], ra, oa), c0, s0); a[2 * i + 1] = fmaf(fmaf(a[2 * i + 1], ra, oa), c1, s1);
        b[2 * i] = fmaf(fmaf(b[2 * i], rb, ob), c0, s0); b[2 * i + 1] = fmaf(fmaf(b[2 * i + 1], rb, ob), c1, s1);
      }
      ln_stats2(a, b, 0.5f, oa, ra, ob, rb);
      CK(22);
#pragma unroll
      for (int i = 0; i < 9; i++) {
        const int k = i == 2 ? 1 : i == 6 ? 2 : 0;
        sts(sh3[k] + i * 512, and_or(pack_bf16(fmaf(a[2 * i], ra, oa), fmaf(a[2 * i + 1], ra, oa)), ham[k], hom[k]));
        sts(sh3[k] + i * 512 + 64, and_or(pack_bf16(fmaf(b[2 * i], rb, ob), fmaf(b[2 * i + 1], rb, ob)), ham[k], hom[k]));
      }
      fence_async_smem();
      if (wp < 2 * H3G) bar_arrive(8, 32 + 64 * H3G); else bar_arrive(9, 288 - 64 * H3G);
      CK(23);
    }
  } else __syncthreads();

  const bool g2 = cta < 130 && (cta >> 1) != 56;
  const int z2 = cta < 112 ? cta : cta - 2, r = z2 >> 6;
  const int s2 = 128 * ((z2 >> 2) & 15), d2 = 144 * (z2 & 3);
  constexpr int ST0 = (32 - JSK - 1) % NST, ST1 = 31 % NST;

  if (wg == 2) {
    asm volatile("setmaxnreg.dec.sync.aligned.u32 40;");
    auto load_b = [&](bool second, int i, int st) {
      const uint32_t lb = full0 + 8 * (B_LAND + st), bytes = second ? 18432 : STAGE - a1bytes;
      mbar_expect(lb, bytes);
      bulk_ld(sbase + (second ? st * STAGE2 + 16384 : st * STAGE + a1bytes),
              second ? sc->u + ((size_t)(36 * r + kb2_order(i)) * D_ + d2) * 128 : sc->h3 + ((size_t)(i * 18 + (d1 >> 5)) << 12), bytes, lb);
    };
    if (wp == 8) {
      int st = rows ? 4 : 0, ph = 1;
#pragma unroll 1
      for (int kb = st; kb < 32; kb++) {
        if (rows && (kb >> 1) == 2) mbar_wait(full0 + 8 * (B_S4 - 4 + kb), 0);
        mbar_wait(empty0 + 8 * st, ph);
        if (elect()) {
          load_a1(st, kb);
          if (kb >= PF2K && kb < PF2K + PF2 && g2)
            prefetch_l2(reinterpret_cast<const uint8_t*>(p.w2) + (size_t)(36 * r + kb2_order(kb - PF2K)) * 262144 + (z2 & 63) * 4096, 4096);
        }
        __syncwarp();
        ring_next<false>(st, ph);
      }
      if (g2) {
        st++;
#pragma unroll 1
        for (int i = 0; i < 36; i++) {
          if (i == HOLDA) mbar_wait(full0 + 8 * B_GO, 0);
          mbar_wait(empty0 + 8 * st, ph);
          if (elect()) {
            mbar_expect(full0 + 8 * st, 16384);
            tma3d_ef(sbase + st * STAGE2, &maps.w2, 64 * (36 * r + kb2_order(i)), s2 >> 6, full0 + 8 * st);
          }
          __syncwarp();
          ring_next<true>(st, ph);
        }
      }
    } else if (wp >= 10) {
      const int sw = wp - 10;
      if (rows) {
        const CUtensorMap* mp = upin(&maps.h3[sw]);
        const uint32_t src = upin(sbase + O_B3 + sw * (H3G * 4608)), c0 = upin(64 * (cta & 15)), c1 = upin(18 * (cta >> 4)), c2 = upin(H3G * sw);
        unsigned* flag = pin(&sc->cnt[C_H3 + (cta >> 4) + 8 * sw]);
        bar_sync(8 + sw, sw ? 288 - 64 * H3G : 32 + 64 * H3G);
        if (sw) mbar_wait(full0 + 8 * H3W, 0);
        if (elect()) {
          tma_st3d(mp, src, c0, c1, c2);
          mbar_arrive(full0 + 8 * B_S4);
          bulk_commit_wait();
          red_add(flag, 1);
          mbar_arrive(full0 + 8 * B_S5);
          TS(sw ? 24 : 13);
        }
        __syncwarp();
      }
      if (sw) {
        if (rows) {
          mbar_wait(full0 + 8 * B_S5, 0);
          if (elect()) { asm volatile("fence.acq_rel.gpu;" ::: "memory"); red_add(&sc->cnt[C_X + 64], 1); }
          __syncwarp();
        }
        if (g2) {
          uint2 v[3];
          int it = 0;
          do {
#pragma unroll
            for (int i = 0; i < 3; i++) v[i] = ld_rlx2(sc->mod + 3 * D_ + d2 + 2 * min(l + 32 * i, 71));
          } while (any(or3(diff2(v[0].x, v[0].y, tag16), diff2(v[1].x, v[1].y, tag16), diff2(v[2].x, v[2].y, tag16)) & 0xffffu) && ++it < SPIN_MAX);
#pragma unroll
          for (int i = 0; i < 3; i++) sts(sbase + O_GB + 4 * min(l + 32 * i, 71), __byte_perm(v[i].x, v[i].y, 0x7632));
          __syncwarp();
        }
        wait_cnt<true>(&sc->cnt[C_X + 64], 128 * ep);
        if (elect()) mbar_arrive(full0 + 8 * B_X);
        __syncwarp();
      }
      uint32_t lph = 0;
      auto check_tiles = [&](bool second, int n, int st, uint32_t o1, uint32_t d2nd) {
        const uint32_t b1 = pin(sbase + o1), b2 = pin(sbase + o1 + d2nd);
        int i = 0, it = 0;
#pragma unroll 1
        do {
          const uint32_t so = st * (second ? STAGE2 : STAGE);
          mbar_wait(full0 + 8 * (B_LAND + st), (lph >> st) & 1);
          lph ^= 1u << st;
          uint32_t v[20];
#pragma unroll
          for (int k = 0; k < 20; k++) if (!second || k < 10 || k >= 12) v[k] = lds(k < 12 ? b1 + so + k * 1024 : b2 + so + (k - 12) * 1024); else v[k] = tag1;
#pragma unroll
          for (int k = 0; k < 10; k++) v[k] = diff2(v[2 * k], v[2 * k + 1], tag1);
          const uint32_t bad = or3(or3(or3(v[0], v[1], v[2]), or3(v[3], v[4], v[5]), v[6]), v[7], or3(v[8], v[9], 0));
          if (__builtin_expect(any(bad & 1) && ++it < SPIN_MAX, 0)) {
            FAILCNT(2 + second);
            fence_async_smem();
            __syncwarp();
            if (elect()) load_b(second, i, st);
            __syncwarp();
            continue;
          }
          if (elect()) mbar_arrive(full0 + 8 * st);
          if (++st == NST) st = 0;
          i++;
        } while (i < n);
      };
      if (!sw) check_tiles(false, NV1, 0, a1bytes + l * 32 + (l >> 2) * 4, helper ? 4096 : 12288);
      const bool first = helper || m1 < W0N;
#pragma unroll 1
      for (int k = sw ? first : !first; k <= sw; k++) {
        const uint32_t stg = sbase + (!k ? ST0 * STAGE : helper ? ST1 * STAGE : O_U1);
        const int kbA = (f1 >> 6) + (helper ? 2 : 1) * (k ^ flip), kbB = helper ? (f1 >> 6) + 1 : kbA;
        uint8_t* const uA = upin(sc->u + ((size_t)kbA * D_ + d1) * 128);
        uint8_t* const uB = upin(sc->u + ((size_t)kbB * D_ + (helper ? d1 : d1 + 96)) * 128);
        unsigned* const fA = pin(&sc->cnt[C_U + kbA]);
        unsigned* const fB = pin(&sc->cnt[C_U + kbB]);
        const bool slow = sw && !helper;
        bar_sync(11 + k, 160);
        if (!slow) { if (elect()) { bulk_st(uA, stg, 96 * 128); TS(k ? 31 : 30); } __syncwarp(); }
        bar_sync(13 + k, 160);
        if (slow) {
          if (g2) mbar_wait(full0 + 8 * B_GO, 0);
          if (first) pause(10 * TRK0);
#pragma unroll 1
          for (int i = 0; i < 20480; i += 2048) {
            if (elect()) bulk_st(uA + i, stg + i, 2048);
            pause(k ? TRKC : TRK0);
          }
        }
        if (elect()) {
          if (helper ? k : !slow) bulk_st(uB, stg + 96 * 128, helper ? 96 * 128 : 64 * 128);
          bulk_commit_wait();
          red_add(fA, 1);
          if (helper && k) red_add(fB, 1);
          if (!k || helper) mbar_arrive(empty0 + 8 * (k ? ST1 : ST0));
          TS(k ? 23 : 17);
          mbar_arrive(full0 + 8 * B_S5);
        }
        __syncwarp();
      }
      if (sw) {
        mbar_wait(full0 + 8 * B_S5, rows);
        if (elect()) { asm volatile("fence.acq_rel.gpu;" ::: "memory"); red_add(&sc->cnt[C_X], 1); }
        __syncwarp();
      }
      if (g2) {
        if (!sw) check_tiles(true, NV2, 3, 16384 + l * 32 + (4 * (g & 1) + (g >> 1)) * 4, 10240);
        else {
          wait_cnt<true>(&sc->cnt[C_X], NCTA * ep);
          if (elect()) {
            mbar_arrive(full0 + 8 * B_X);
            if (cta == 0) sc->cnt[C_EP] = ep;
          }
          __syncwarp();
        }
      }
      __syncwarp();
    } else {
      uint64_t ready = 0;
      int st = 0, ph = 1;
#pragma unroll 1
      for (int kb = 0; kb < 32; kb++) {
        const uint8_t* src = upin(sc->h3 + ((size_t)(kb * 18 + (d1 >> 5)) << 12));
        const uint32_t dst = upin(sbase + st * STAGE + a1bytes), lb = full0 + 8 * ((kb < NV1 ? B_LAND : 0) + st);
        if (kb == NV1) { mbar_wait(full0 + 8 * B_X, 0); fence_async_glb(); ready = ~0ull; }
        if (rows && (kb >> 1) == 2) mbar_wait(full0 + 8 * (B_S4 - 4 + kb), 0);
        mbar_wait(empty0 + 8 * st, ph);
        if (elect()) mbar_expect(lb, STAGE - a1bytes);
        wait_flags(sc->cnt + C_H3, 32, (kb & 7) + (kb < 8 * H3G ? 0 : 8), 16 * ep, ready);
        if (elect()) bulk_ld(dst, src, STAGE - a1bytes, lb);
        ring_next<false>(st, ph);
      }
      if (g2) {
        ready = 0;
        st++;
#pragma unroll 1
        for (int i = 0; i < 36; i++) {
          const int kb = kb2_order(i);
          const uint8_t* src = upin(sc->u + ((size_t)(36 * r + kb) * D_ + d2) * 128);
          const uint32_t dst = upin(sbase + st * STAGE2 + 16384), lb = full0 + 8 * ((i < NV2 ? B_LAND : 0) + st);
          if (i == NV2) { mbar_wait(full0 + 8 * B_X, 1); fence_async_glb(); ready = ~0ull; }
          mbar_wait(empty0 + 8 * st, ph);
          if (elect()) mbar_expect(lb, 18432);
          wait_flags(sc->cnt + C_U + 36 * r, 36, kb, 4 * ep, ready);
          if (elect()) {
            bulk_ld(dst, src, 18432, lb);
            if (i == GOAT) mbar_arrive(full0 + 8 * B_GO);
          }
          ring_next<true>(st, ph);
        }
      }
    }
  } else {
    asm volatile("setmaxnreg.inc.sync.aligned.u32 232;");
    const int wgu = wg;
    constexpr uint32_t sb4 = sbase >> 4;
    const int w = wp & 3;
    Ring rg = {0, 0};
    uint32_t* const x1p = p.out + (size_t)(cta + 256 * wp) * 288 + l;
    const uint32_t ad = pin(sbase + (!wg ? ST0 * STAGE : helper ? ST1 * STAGE : O_U1) + (8 * (l >> 4) + (l & 7)) * 128 + (((2 * w + ((l >> 3) & 1)) ^ (l & 7)) << 4));
    const uint32_t uam = pin(g == 2 * t ? 0xfffefffeu : ~0u), uom = pin(g == 2 * t ? tag1 * 0x10001u : 0u);
    float acc[96];
    constexpr uint32_t LA = (8192 >> 4) << 16, LB = (4096 >> 4) << 16;
    {
      const int fa = f1 + (helper ? 128 : 64) * (wg ^ flip) + 16 * w + g, fb = helper ? f1 + 64 + 16 * w + g : fa;
      const float a0 = 0.5f * __bfloat162float(p.b1[fa]), a1 = 0.5f * __bfloat162float(p.b1[fa + 8]);
      const float b0 = 0.5f * __bfloat162float(p.b1[fb]), b1 = 0.5f * __bfloat162float(p.b1[fb + 8]);
#pragma unroll
      for (int i = 0; i < 96; i++) acc[i] = i < 48 ? ((i & 2) ? a1 : a0) : ((i & 2) ? b1 : b0);
      reg_fence(acc);
    }
    if (!helper) gemm_main<0>(acc, sb4 + (wgu ^ flip) * 512 + LA, 0, sb4 + 1024 + LB, wgu, rg, x1p, xr);
    else {
      float ac2[96];
#pragma unroll
      for (int i = 0; i < 96; i++) asm volatile("mov.b32 %0, %1;" : "=f"(ac2[i]) : "f"(acc[i]));
      gemm_main<1>(ac2, sb4 + (wgu ^ flip) * 1024 + LA, sb4 + 512 + LA, sb4 + 1536 + LB, wgu, rg, x1p, xr);
#pragma unroll
      for (int i = 0; i < 96; i++) asm volatile("mov.b32 %0, %1;" : "=f"(acc[i]) : "f"(ac2[i]));
    }
    if (t128 == 0) TS(wg ? 16 : 6);
    {
      float tp[2] = {0.f, 0.f};
#pragma unroll
      for (int j = 0; j < 12; j++) {
        const float* a = &acc[8 * j];
        const float k3 = j < 2 ? GK3 : fmaf(tp[j & 1], 0.0f, GK3);
        float o[8];
#pragma unroll
        for (int e = 0; e < 8; e++) {
          float z = a[e] * fmaf(a[e] * k3, a[e], GK1);
          asm("tanh.approx.f32 %0, %0;" : "+f"(z));
          if (e == GDEP) tp[j & 1] = z;
          o[e] = fmaf(a[e], z, a[e]);
        }
        stmatrix4t(ad + j * 2048, and_or(pack_bf16(o[0], o[1]), uam, uom), pack_bf16(o[2], o[3]), and_or(pack_bf16(o[4], o[5]), uam, uom), pack_bf16(o[6], o[7]));
        if (j == 5) {
          fence_async_smem();
          bar_arrive(11 + wgu, 160);
        }
        if ((j == 5 && helper && !wgu) || (j == 9 && !helper)) break;
      }
      fence_async_smem();
      bar_arrive(13 + wgu, 160);
      if (t128 == 0) TS(wg ? 29 : 28);
    }
    if (g2) {
      const int mb = wgu ^ r;
      const int odd = z2 & 1;
      uint4 gq[4];
      uint2 gs;
      {
        float a0 = 0.f, a1 = 0.f;
        if (wgu) { a0 = __bfloat162float(p.b2[s2 + 64 * mb + 16 * w + g]); a1 = __bfloat162float(p.b2[s2 + 64 * mb + 16 * w + 8 + g]); }
#pragma unroll
        for (int i = 0; i < 4; i++) gq[i] = lds4(sbase + O_GB + 32 * odd + 64 * i + 16 * t);
        gs = lds2(sbase + O_GB + (odd ? 0 : 256) + 8 * t);
#pragma unroll
        for (int i = 0; i < 72; i++) acc[i] = (i & 2) ? a1 : a0;
      }
      uint32_t* const ob = p.out + (size_t)(s2 + 64 * mb + 16 * w + g) * 288 + (d2 >> 1);
      uint32_t* const oq = pin(ob + 8 * odd + 4 * t);
      uint32_t* const os = pin(ob + (odd ? 0 : 64) + 2 * t);
      rg.st++;
      gemm_main<3>(acc, sb4 + mb * 512 + LA, 0, sb4 + 1024 + (1 << 16), wgu, rg, x1p, xr);
      if (t128 == 0) TS(wg ? 20 : 19);
      auto finish = [&](const float* aq, const float* as) {
#pragma unroll
        for (int i = 0; i < 8; i++) {
          const float* a = aq + 16 * (i >> 1) + 2 * (i & 1);
          const uint4 gv = gq[i >> 1];
          red_bf16x8(oq + (i & 1) * 2304 + 16 * (i >> 1), hmul2(gv.x, pack_bf16(a[0], a[1])), hmul2(gv.y, pack_bf16(a[4], a[5])),
                     hmul2(gv.z, pack_bf16(a[8], a[9])), hmul2(gv.w, pack_bf16(a[12], a[13])));
        }
#pragma unroll
        for (int i = 0; i < 2; i++) red_bf16x4(os + i * 2304, hmul2(gs.x, pack_bf16(as[2 * i], as[2 * i + 1])), hmul2(gs.y, pack_bf16(as[2 * i + 4], as[2 * i + 5])));
      };
      if (odd) finish(&acc[8], &acc[0]); else finish(&acc[0], &acc[64]);
      if (t128 == 0) TS(wg ? 7 : 21);
      __syncwarp();
    }
  }
}

typedef CUresult (*EncodeFn)(CUtensorMap*, CUtensorMapDataType, cuuint32_t, void*, const cuuint64_t*, const cuuint64_t*, const cuuint32_t*,
                             const cuuint32_t*, CUtensorMapInterleave, CUtensorMapSwizzle, CUtensorMapL2promotion, CUtensorMapFloatOOBfill);

struct Dim { cuuint64_t n, stride; cuuint32_t box; };
template <int RANK>
void make_map(EncodeFn enc, CUtensorMap* m, bool words, int swz, const void* ptr, const Dim (&d)[RANK]) {
  cuuint64_t gd[RANK], gs[RANK];
  cuuint32_t bx[RANK], es[RANK];
  for (int i = 0; i < RANK; i++) { gd[i] = d[i].n; gs[i] = d[i].stride; bx[i] = d[i].box; es[i] = 1; }
  enc(m, words ? CU_TENSOR_MAP_DATA_TYPE_UINT32 : CU_TENSOR_MAP_DATA_TYPE_BFLOAT16, RANK, const_cast<void*>(ptr), gd, gs + 1, bx, es,
      CU_TENSOR_MAP_INTERLEAVE_NONE, static_cast<CUtensorMapSwizzle>(swz),
      swz == 3 ? CU_TENSOR_MAP_L2_PROMOTION_L2_256B : CU_TENSOR_MAP_L2_PROMOTION_NONE, CU_TENSOR_MAP_FLOAT_OOB_FILL_NONE);
}

}

extern "C" void kernel_launch(void* const* d_in, const int* in_sizes, int n_in, void* d_out, int out_size) {
  (void)in_sizes; (void)n_in; (void)out_size;
  static EncodeFn enc = nullptr;
  static void *sptr = nullptr, *tptr = nullptr;
  if (!enc) {
    void* f = nullptr; cudaDriverEntryPointQueryResult qr;
    cudaGetDriverEntryPoint("cuTensorMapEncodeTiled", &f, cudaEnableDefault, &qr);
    enc = reinterpret_cast<EncodeFn>(f);
    cudaFuncSetAttribute(fused_kernel, cudaFuncAttributeMaxDynamicSharedMemorySize, SMEM_BYTES);
    cudaGetSymbolAddress(&sptr, g_s);
    cudaGetSymbolAddress(&tptr, T_TAB);
  }
  Params p;
  p.x = (const __nv_bfloat16*)d_in[0]; p.wr = (const __nv_bfloat16*)d_in[1]; p.wi = (const __nv_bfloat16*)d_in[2];
  p.b1 = (const __nv_bfloat16*)d_in[5]; p.b2 = (const __nv_bfloat16*)d_in[7];
  p.c = (const __nv_bfloat16*)d_in[8]; p.wmod = (const __nv_bfloat16*)d_in[9];
  p.w1 = (const __nv_bfloat16*)d_in[4]; p.w2 = (const __nv_bfloat16*)d_in[6];
  p.out = static_cast<uint32_t*>(d_out); p.s = static_cast<Scratch*>(sptr); p.tab = static_cast<const uint4*>(tptr);
  Maps maps;
  make_map<4>(enc, &maps.w1a, false, 3, p.w1, {{64, 0, 64}, {16, 128 * 2 * F_, 4}, {128, 2 * F_, 16}, {72, 128, 2}});
  make_map<4>(enc, &maps.w1b, false, 3, p.w1, {{64, 0, 64}, {16, 128 * 2 * F_, 4}, {128, 2 * F_, 16}, {72, 128, 3}});
  make_map<3>(enc, &maps.w2, false, 3, p.w2, {{64, 0, 64}, {F_, 2 * S_, 64}, {32, 128, 2}});
  make_map<2>(enc, &maps.z1, true, 0, p.s->z1, {{5120, 0, 40}, {120, 20480, 60}});
  for (int i = 0; i < 2; i++) make_map<2>(enc, &maps.z2[i], true, 0, p.s->z2, {{4800, 0, i ? 16u : 24u}, {128, 19200, 128}});
  for (int i = 0; i < 4; i++) make_map<2>(enc, &maps.wf[i], false, 2 - (i & 1), (i & 2) ? p.wi : p.wr, {{16 * DF_, 0, (i & 1) ? 16u : 32u}, {128, 32 * DF_, 128}});
  make_map<2>(enc, &maps.wm, false, 1, p.wmod, {{6 * D_, 0, 16}, {D_, 12 * D_, 192}});
  for (int i = 0; i < 2; i++) make_map<3>(enc, &maps.h3[i], true, 0, p.s->h3, {{1024, 0, 64}, {144, 4096, 18}, {4, 144 * 4096, i ? 4u - H3G : H3G}});
  fused_kernel<<<NCTA, NTHR, SMEM_BYTES, cudaStreamPerThread>>>(p, maps);
}
```

```cpp
#include <cuda_runtime.h>
#include <cuda_bf16.h>
#include <cuda.h>
#include <stdint.h>

namespace {

constexpr int S_ = 2048, D_ = 576, DF_ = 289, F_ = 4608;
constexpr int NCTA = 132, NTHR = 384;
constexpr int STAGE = 36864, NST = 6;
constexpr int STAGE2 = 34816, O_U1 = NST * STAGE2, O_GB = O_U1 + 20480, SMEM_BYTES = 232448;
constexpr uint32_t sbase = 1024, red = sbase + NST * STAGE, full0 = sbase + SMEM_BYTES - 256, empty0 = full0 + 8 * NST;
constexpr int O_NRM = 0, O_B1 = 19456, O_Z1 = 38912, O_P2 = 59392, O_ST = 3 * STAGE;
constexpr int O_RAW = 4 * STAGE;
constexpr int O_IN = 4 * STAGE, O_Y = O_IN + 19456, O_B3 = O_IN + 38912, O_MOD = O_IN + 57344;

__device__ __align__(128) const uint32_t T_TAB[5632] = {
0x3f803f80,0xbf803f80,0x3f803f80,0xbf803f80,0x3f803f80,0xbf803f80,0x3f803f80,0xbf803f80,0x3f803f80,0xbf803f80,0x3f803f80,0xbf803f80,
0x3f803f80,0xbf803f80,0x3f803f80,0xbf803f80,0x3f7f3f80,0xbdc90000,0x3f223f35,0xbf46bf35,0x3f753f7b,0xbe95be48,0x3ef13f0e,0xbf62bf55,
0x3f623f6d,0xbef1bec4,0x3e953ec4,0xbf75bf6d,0x3f463f55,0xbf22bf0e,0x3dc93e48,0xbf7fbf7b,0x3f7b3f80,0xbe480000,0xbe480000,0xbf7bbf80,
0x3f553f6d,0xbf0ebec4,0xbf0ebec4,0xbf55bf6d,0x3f0e3f35,0xbf55bf35,0xbf55bf35,0xbf0ebf35,0x3e483ec4,0xbf7bbf6d,0xbf7bbf6d,0xbe48bec4,
0x3f753f80,0xbe950000,0xbf62bf35,0xbef1bf35,0x3f223f55,0xbf46bf0e,0xbf7fbf7b,0x3dc9be48,0x3dc93ec4,0xbf7fbf6d,0xbf46bf6d,0x3f223ec4,
0xbef1be48,0xbf62bf7b,0xbe95bf0e,0x3f753f55,0x3f6d3f80,0xbec40000,0xbf6dbf80,0x3ec40000,0x3ec43f35,0xbf6dbf35,0xbec4bf35,0x3f6d3f35,
0xbec40000,0xbf6dbf80,0x3ec40000,0x3f6d3f80,0xbf6dbf35,0xbec4bf35,0x3f6d3f35,0x3ec43f35,0x3f623f80,0xbef10000,0xbe95bf35,0x3f753f35,
0x3dc93f0e,0xbf7fbf55,0x3f223e48,0x3f463f7b,0xbf46bec4,0xbf22bf6d,0x3f7f3f6d,0xbdc93ec4,0xbf75bf7b,0x3e95be48,0x3ef13f55,0xbf62bf0e,
0x3f553f80,0xbf0e0000,0x3f0e0000,0x3f553f80,0xbe483ec4,0xbf7bbf6d,0x3f7b3f6d,0xbe483ec4,0xbf7bbf35,0xbe48bf35,0x3e483f35,0xbf7bbf35,
0xbf0ebf6d,0x3f553ec4,0xbf55bec4,0xbf0ebf6d,0x3f463f80,0xbf220000,0x3f7f3f35,0x3dc93f35,0xbef13e48,0xbf62bf7b,0x3e953f55,0xbf75bf0e,
0xbf75bf6d,0x3e95bec4,0xbf62bec4,0xbef1bf6d,0x3dc9bf0e,0x3f7f3f55,0xbf22bf7b,0x3f463e48,0x3f353f80,0xbf350000,0x3f353f80,0xbf350000,
0xbf350000,0xbf35bf80,0xbf350000,0xbf35bf80,0xbf35bf80,0x3f350000,0xbf35bf80,0x3f350000,0x3f350000,0x3f353f80,0x3f350000,0x3f353f80,
0x3f223f80,0xbf460000,0xbdc93f35,0xbf7fbf35,0xbf62be48,0xbef1bf7b,0xbf75bf55,0x3e95bf0e,0xbe95bf6d,0x3f753ec4,0x3ef1bec4,0x3f623f6d,
0x3f7f3f0e,0x3dc93f55,0x3f463f7b,0xbf223e48,0x3f0e3f80,0xbf550000,0xbf550000,0xbf0ebf80,0xbf7bbec4,0xbe48bf6d,0xbe48bf6d,0x3f7b3ec4,
0x3e48bf35,0x3f7b3f35,0x3f7b3f35,0xbe483f35,0x3f553f6d,0xbf0e3ec4,0xbf0e3ec4,0xbf55bf6d,0x3ef13f80,0xbf620000,0xbf75bf35,0x3e95bf35,
0xbf7fbf0e,0x3dc9bf55,0x3f46be48,0x3f223f7b,0x3f22bec4,0x3f463f6d,0x3dc93f6d,0xbf7fbec4,0x3e953f7b,0xbf75be48,0xbf62bf55,0x3ef1bf0e,
0x3ec43f80,0xbf6d0000,0xbec4bf80,0x3f6d0000,0xbf6dbf35,0x3ec4bf35,0x3f6d3f35,0xbec43f35,0x3f6d0000,0x3ec43f80,0xbf6d0000,0xbec4bf80,
0xbec43f35,0xbf6dbf35,0x3ec4bf35,0x3f6d3f35,0x3e953f80,0xbf750000,0x3ef1bf35,0x3f623f35,0xbf46bf55,0x3f22bf0e,0x3dc93f7b,0xbf7fbe48,
0x3f7f3ec4,0xbdc93f6d,0xbf22bf6d,0x3f46bec4,0xbf623e48,0xbef1bf7b,0x3f753f0e,0xbe953f55,0x3e483f80,0xbf7b0000,0x3f7b0000,0x3e483f80,
0xbf0ebf6d,0x3f55bec4,0xbf553ec4,0xbf0ebf6d,0x3f553f35,0xbf0e3f35,0x3f0ebf35,0x3f553f35,0xbf7bbec4,0x3e48bf6d,0xbe483f6d,0xbf7bbec4,
0x3dc93f80,0xbf7f0000,0x3f463f35,0xbf223f35,0xbe95bf7b,0x3f75be48,0xbf62bf0e,0x3ef1bf55,0x3ef13f6d,0xbf623ec4,0x3f753ec4,0xbe953f6d,
0xbf22bf55,0x3f46bf0e,0xbf7fbe48,0x3dc9bf7b,0x3f80,0xbf800000,0x3f80,0xbf800000,0xbf80,0x3f800000,0xbf80,0x3f800000,
0x3f80,0xbf800000,0x3f80,0xbf800000,0xbf80,0x3f800000,0xbf80,0x3f800000,0xbdc93f80,0xbf7f0000,0xbf463f35,0xbf22bf35,
0x3e95bf7b,0x3f753e48,0x3f62bf0e,0x3ef13f55,0xbef13f6d,0xbf62bec4,0xbf753ec4,0xbe95bf6d,0x3f22bf55,0x3f463f0e,0x3f7fbe48,0x3dc93f7b,
0xbe483f80,0xbf7b0000,0xbf7b0000,0x3e48bf80,0x3f0ebf6d,0x3f553ec4,0x3f553ec4,0xbf0e3f6d,0xbf553f35,0xbf0ebf35,0xbf0ebf35,0x3f55bf35,
0x3f7bbec4,0x3e483f6d,0x3e483f6d,0xbf7b3ec4,0xbe953f80,0xbf750000,0xbef1bf35,0x3f62bf35,0x3f46bf55,0x3f223f0e,0xbdc93f7b,0xbf7f3e48,
0xbf7f3ec4,0xbdc9bf6d,0x3f22bf6d,0x3f463ec4,0x3f623e48,0xbef13f7b,0xbf753f0e,0xbe95bf55,0xbec43f80,0xbf6d0000,0x3ec4bf80,0x3f6d0000,
0x3f6dbf35,0x3ec43f35,0xbf6d3f35,0xbec4bf35,0xbf6d0000,0x3ec4bf80,0x3f6d0000,0xbec43f80,0x3ec43f35,0xbf6d3f35,0xbec4bf35,0x3f6dbf35,
0xbef13f80,0xbf620000,0x3f75bf35,0x3e953f35,0x3f7fbf0e,0x3dc93f55,0xbf46be48,0x3f22bf7b,0xbf22bec4,0x3f46bf6d,0xbdc93f6d,0xbf7f3ec4,
0xbe953f7b,0xbf753e48,0x3f62bf55,0x3ef13f0e,0xbf0e3f80,0xbf550000,0x3f550000,0xbf0e3f80,0x3f7bbec4,0xbe483f6d,0x3e48bf6d,0x3f7bbec4,
0xbe48bf35,0x3f7bbf35,0xbf7b3f35,0xbe48bf35,0xbf553f6d,0xbf0ebec4,0x3f0e3ec4,0xbf553f6d,0xbf223f80,0xbf460000,0x3dc93f35,0xbf7f3f35,
0x3f62be48,0xbef13f7b,0x3f75bf55,0x3e953f0e,0x3e95bf6d,0x3f75bec4,0xbef1bec4,0x3f62bf6d,0xbf7f3f0e,0x3dc9bf55,0xbf463f7b,0xbf22be48,
0xbf353f80,0xbf350000,0xbf353f80,0xbf350000,0x3f350000,0xbf353f80,0x3f350000,0xbf353f80,0x3f35bf80,0x3f350000,0x3f35bf80,0x3f350000,
0xbf350000,0x3f35bf80,0xbf350000,0x3f35bf80,0xbf463f80,0xbf220000,0xbf7f3f35,0x3dc9bf35,0x3ef13e48,0xbf623f7b,0xbe953f55,0xbf753f0e,
0x3f75bf6d,0x3e953ec4,0x3f62bec4,0xbef13f6d,0xbdc9bf0e,0x3f7fbf55,0x3f22bf7b,0x3f46be48,0xbf553f80,0xbf0e0000,0xbf0e0000,0x3f55bf80,
0x3e483ec4,0xbf7b3f6d,0xbf7b3f6d,0xbe48bec4,0x3f7bbf35,0xbe483f35,0xbe483f35,0xbf7b3f35,0x3f0ebf6d,0x3f55bec4,0x3f55bec4,0xbf0e3f6d,
0xbf623f80,0xbef10000,0x3e95bf35,0x3f75bf35,0xbdc93f0e,0xbf7f3f55,0xbf223e48,0x3f46bf7b,0x3f46bec4,0xbf223f6d,0xbf7f3f6d,0xbdc9bec4,
0x3f75bf7b,0x3e953e48,0xbef13f55,0xbf623f0e,0xbf6d3f80,0xbec40000,0x3f6dbf80,0x3ec40000,0xbec43f35,0xbf6d3f35,0x3ec4bf35,0x3f6dbf35,
0x3ec40000,0xbf6d3f80,0xbec40000,0x3f6dbf80,0x3f6dbf35,0xbec43f35,0xbf6d3f35,0x3ec4bf35,0xbf753f80,0xbe950000,0x3f62bf35,0xbef13f35,
0xbf223f55,0xbf463f0e,0x3f7fbf7b,0x3dc93e48,0xbdc93ec4,0xbf7f3f6d,0x3f46bf6d,0x3f22bec4,0x3ef1be48,0xbf623f7b,0x3e95bf0e,0x3f75bf55,
0xbf7b3f80,0xbe480000,0x3e480000,0xbf7b3f80,0xbf553f6d,0xbf0e3ec4,0x3f0ebec4,0xbf553f6d,0xbf0e3f35,0xbf553f35,0x3f55bf35,0xbf0e3f35,
0xbe483ec4,0xbf7b3f6d,0x3f7bbf6d,0xbe483ec4,0xbf7f3f80,0xbdc90000,0xbf223f35,0xbf463f35,0xbf753f7b,0xbe953e48,0xbef13f0e,0xbf623f55,
0xbf623f6d,0xbef13ec4,0xbe953ec4,0xbf753f6d,0xbf463f55,0xbf223f0e,0xbdc93e48,0xbf7f3f7b,0x3f803f80,0xbf803f80,0x3f803f80,0xbf803f80,
0x3f803f80,0xbf803f80,0x3f803f80,0xbf803f80,0x3f803f80,0xbf803f80,0x3f803f80,0xbf803f80,0x3f803f80,0xbf803f80,0x3f803f80,0xbf803f80,
0xbdc90000,0xbf7fbf80,0xbf46bf35,0xbf22bf35,0xbe95be48,0xbf75bf7b,0xbf62bf55,0xbef1bf0e,0xbef1bec4,0xbf62bf6d,0xbf75bf6d,0xbe95bec4,
0xbf22bf0e,0xbf46bf55,0xbf7fbf7b,0xbdc9be48,0xbf7bbf80,0x3e480000,0x3e480000,0x3f7b3f80,0xbf55bf6d,0x3f0e3ec4,0x3f0e3ec4,0x3f553f6d,
0xbf0ebf35,0x3f553f35,0x3f553f35,0x3f0e3f35,0xbe48bec4,0x3f7b3f6d,0x3f7b3f6d,0x3e483ec4,0x3e950000,0x3f753f80,0x3ef13f35,0xbf62bf35,
0x3f463f0e,0x3f223f55,0xbdc93e48,0xbf7fbf7b,0x3f7f3f6d,0x3dc93ec4,0xbf22bec4,0xbf46bf6d,0x3f623f7b,0xbef1be48,0xbf75bf55,0xbe95bf0e,
0x3f6d3f80,0xbec40000,0xbf6dbf80,0x3ec40000,0x3ec43f35,0xbf6dbf35,0xbec4bf35,0x3f6d3f35,0xbec40000,0xbf6dbf80,0x3ec40000,0x3f6d3f80,
0xbf6dbf35,0xbec4bf35,0x3f6d3f35,0x3ec43f35,0xbef10000,0xbf62bf80,0x3f753f35,0x3e953f35,0xbf7fbf55,0xbdc9bf0e,0x3f463f7b,0xbf22be48,
0xbf22bf6d,0x3f463ec4,0xbdc93ec4,0xbf7fbf6d,0x3e95be48,0x3f753f7b,0xbf62bf0e,0xbef1bf55,0xbf55bf80,0x3f0e0000,0xbf0e0000,0xbf55bf80,
0x3e48bec4,0x3f7b3f6d,0xbf7bbf6d,0x3e48bec4,0x3f7b3f35,0x3e483f35,0xbe48bf35,0x3f7b3f35,0x3f0e3f6d,0xbf55bec4,0x3f553ec4,0x3f0e3f6d,
0x3f220000,0x3f463f80,0xbdc9bf35,0x3f7f3f35,0x3f623f7b,0xbef13e48,0x3f753f0e,0x3e953f55,0xbe953ec4,0xbf75bf6d,0x3ef13f6d,0xbf62bec4,
0xbf7fbf55,0x3dc9bf0e,0xbf46be48,0xbf22bf7b,0x3f353f80,0xbf350000,0x3f353f80,0xbf350000,0xbf350000,0xbf35bf80,0xbf350000,0xbf35bf80,
0xbf35bf80,0x3f350000,0xbf35bf80,0x3f350000,0x3f350000,0x3f353f80,0x3f350000,0x3f353f80,0xbf460000,0xbf22bf80,0xbf7fbf35,0x3dc9bf35,
0xbef1bf7b,0x3f623e48,0x3e95bf0e,0x3f753f55,0x3f753ec4,0x3e953f6d,0x3f623f6d,0xbef13ec4,0x3dc93f55,0xbf7fbf0e,0xbf223e48,0xbf46bf7b,
0xbf0ebf80,0x3f550000,0x3f550000,0x3f0e3f80,0x3f7b3ec4,0x3e483f6d,0x3e483f6d,0xbf7bbec4,0xbe483f35,0xbf7bbf35,0xbf7bbf35,0x3e48bf35,
0xbf55bf6d,0x3f0ebec4,0x3f0ebec4,0x3f553f6d,0x3f620000,0x3ef13f80,0xbe953f35,0xbf75bf35,0xbdc93f55,0xbf7fbf0e,0xbf22bf7b,0x3f46be48,
0xbf46bf6d,0x3f22bec4,0x3f7f3ec4,0x3dc93f6d,0x3f753e48,0x3e953f7b,0xbef13f0e,0xbf62bf55,0x3ec43f80,0xbf6d0000,0xbec4bf80,0x3f6d0000,
0xbf6dbf35,0x3ec4bf35,0x3f6d3f35,0xbec43f35,0x3f6d0000,0x3ec43f80,0xbf6d0000,0xbec4bf80,0xbec43f35,0xbf6dbf35,0x3ec4bf35,0x3f6d3f35,
0xbf750000,0xbe95bf80,0x3f623f35,0xbef13f35,0x3f22bf0e,0x3f463f55,0xbf7fbe48,0xbdc9bf7b,0xbdc93f6d,0xbf7fbec4,0x3f46bec4,0x3f223f6d,
0xbef1bf7b,0x3f62be48,0xbe953f55,0xbf75bf0e,0xbe48bf80,0x3f7b0000,0xbf7b0000,0xbe48bf80,0x3f0e3f6d,0xbf553ec4,0x3f55bec4,0x3f0e3f6d,
0xbf55bf35,0x3f0ebf35,0xbf0e3f35,0xbf55bf35,0x3f7b3ec4,0xbe483f6d,0x3e48bf6d,0x3f7b3ec4,0x3f7f0000,0x3dc93f80,0x3f22bf35,0x3f463f35,
0xbf753e48,0xbe95bf7b,0xbef13f55,0xbf62bf0e,0x3f62bec4,0x3ef13f6d,0x3e95bf6d,0x3f753ec4,0xbf463f0e,0xbf22bf55,0xbdc93f7b,0xbf7fbe48,
0x3f80,0xbf800000,0x3f80,0xbf800000,0xbf80,0x3f800000,0xbf80,0x3f800000,0x3f80,0xbf800000,0x3f80,0xbf800000,
0xbf80,0x3f800000,0xbf80,0x3f800000,0xbf7f0000,0x3dc9bf80,0xbf22bf35,0x3f46bf35,0x3f753e48,0xbe953f7b,0x3ef13f55,0xbf623f0e,
0xbf62bec4,0x3ef1bf6d,0xbe95bf6d,0x3f75bec4,0x3f463f0e,0xbf223f55,0x3dc93f7b,0xbf7f3e48,0x3e48bf80,0x3f7b0000,0x3f7b0000,0xbe483f80,
0xbf0e3f6d,0xbf55bec4,0xbf55bec4,0x3f0ebf6d,0x3f55bf35,0x3f0e3f35,0x3f0e3f35,0xbf553f35,0xbf7b3ec4,0xbe48bf6d,0xbe48bf6d,0x3f7bbec4,
0x3f750000,0xbe953f80,0xbf623f35,0xbef1bf35,0xbf22bf0e,0x3f46bf55,0x3f7fbe48,0xbdc93f7b,0x3dc93f6d,0xbf7f3ec4,0xbf46bec4,0x3f22bf6d,
0x3ef1bf7b,0x3f623e48,0x3e953f55,0xbf753f0e,0xbec43f80,0xbf6d0000,0x3ec4bf80,0x3f6d0000,0x3f6dbf35,0x3ec43f35,0xbf6d3f35,0xbec4bf35,
0xbf6d0000,0x3ec4bf80,0x3f6d0000,0xbec43f80,0x3ec43f35,0xbf6d3f35,0xbec4bf35,0x3f6dbf35,0xbf620000,0x3ef1bf80,0x3e953f35,0xbf753f35,
0x3dc93f55,0xbf7f3f0e,0x3f22bf7b,0x3f463e48,0x3f46bf6d,0x3f223ec4,0xbf7f3ec4,0x3dc9bf6d,0xbf753e48,0x3e95bf7b,0x3ef13f0e,0xbf623f55,
0x3f0ebf80,0x3f550000,0xbf550000,0x3f0ebf80,0xbf7b3ec4,0x3e48bf6d,0xbe483f6d,0xbf7b3ec4,0x3e483f35,0xbf7b3f35,0x3f7bbf35,0x3e483f35,
0x3f55bf6d,0x3f0e3ec4,0xbf0ebec4,0x3f55bf6d,0x3f460000,0xbf223f80,0x3f7fbf35,0x3dc93f35,0x3ef1bf7b,0x3f62be48,0xbe95bf0e,0x3f75bf55,
0xbf753ec4,0x3e95bf6d,0xbf623f6d,0xbef1bec4,0xbdc93f55,0xbf7f3f0e,0x3f223e48,0xbf463f7b,0xbf353f80,0xbf350000,0xbf353f80,0xbf350000,
0x3f350000,0xbf353f80,0x3f350000,0xbf353f80,0x3f35bf80,0x3f350000,0x3f35bf80,0x3f350000,0xbf350000,0x3f35bf80,0xbf350000,0x3f35bf80,
0xbf220000,0x3f46bf80,0x3dc9bf35,0x3f7fbf35,0xbf623f7b,0xbef1be48,0xbf753f0e,0x3e95bf55,0x3e953ec4,0xbf753f6d,0xbef13f6d,0xbf623ec4,
0x3f7fbf55,0x3dc93f0e,0x3f46be48,0xbf223f7b,0x3f55bf80,0x3f0e0000,0x3f0e0000,0xbf553f80,0xbe48bec4,0x3f7bbf6d,0x3f7bbf6d,0x3e483ec4,
0xbf7b3f35,0x3e48bf35,0x3e48bf35,0x3f7bbf35,0xbf0e3f6d,0xbf553ec4,0xbf553ec4,0x3f0ebf6d,0x3ef10000,0xbf623f80,0xbf753f35,0x3e95bf35,
0x3f7fbf55,0xbdc93f0e,0xbf463f7b,0xbf223e48,0x3f22bf6d,0x3f46bec4,0x3dc93ec4,0xbf7f3f6d,0xbe95be48,0x3f75bf7b,0x3f62bf0e,0xbef13f55,
0xbf6d3f80,0xbec40000,0x3f6dbf80,0x3ec40000,0xbec43f35,0xbf6d3f35,0x3ec4bf35,0x3f6dbf35,0x3ec40000,0xbf6d3f80,0xbec40000,0x3f6dbf80,
0x3f6dbf35,0xbec43f35,0xbf6d3f35,0x3ec4bf35,0xbe950000,0x3f75bf80,0xbef13f35,0xbf623f35,0xbf463f0e,0x3f22bf55,0x3dc93e48,0xbf7f3f7b,
0xbf7f3f6d,0x3dc9bec4,0x3f22bec4,0xbf463f6d,0xbf623f7b,0xbef13e48,0x3f75bf55,0xbe953f0e,0x3f7bbf80,0x3e480000,0xbe480000,0x3f7bbf80,
0x3f55bf6d,0x3f0ebec4,0xbf0e3ec4,0x3f55bf6d,0x3f0ebf35,0x3f55bf35,0xbf553f35,0x3f0ebf35,0x3e48bec4,0x3f7bbf6d,0xbf7b3f6d,0x3e48bec4,
0x3dc90000,0xbf7f3f80,0x3f46bf35,0xbf223f35,0x3e95be48,0xbf753f7b,0x3f62bf55,0xbef13f0e,0x3ef1bec4,0xbf623f6d,0x3f75bf6d,0xbe953ec4,
0x3f22bf0e,0xbf463f55,0x3f7fbf7b,0xbdc93e48,0x3f803f80,0xbf803f80,0x3f803f80,0xbf803f80,0x3f803f80,0xbf803f80,0x3f803f80,0xbf803f80,
0x3f803f80,0xbf803f80,0x3f803f80,0xbf803f80,0x3f803f80,0xbf803f80,0x3f803f80,0xbf803f80,0xbf7fbf80,0x3dc90000,0xbf22bf35,0x3f463f35,
0xbf75bf7b,0x3e953e48,0xbef1bf0e,0x3f623f55,0xbf62bf6d,0x3ef13ec4,0xbe95bec4,0x3f753f6d,0xbf46bf55,0x3f223f0e,0xbdc9be48,0x3f7f3f7b,
0x3f7b3f80,0xbe480000,0xbe480000,0xbf7bbf80,0x3f553f6d,0xbf0ebec4,0xbf0ebec4,0xbf55bf6d,0x3f0e3f35,0xbf55bf35,0xbf55bf35,0xbf0ebf35,
0x3e483ec4,0xbf7bbf6d,0xbf7bbf6d,0xbe48bec4,0xbf75bf80,0x3e950000,0x3f623f35,0x3ef13f35,0xbf22bf55,0x3f463f0e,0x3f7f3f7b,0xbdc93e48,
0xbdc9bec4,0x3f7f3f6d,0x3f463f6d,0xbf22bec4,0x3ef13e48,0x3f623f7b,0x3e953f0e,0xbf75bf55,0x3f6d3f80,0xbec40000,0xbf6dbf80,0x3ec40000,
0x3ec43f35,0xbf6dbf35,0xbec4bf35,0x3f6d3f35,0xbec40000,0xbf6dbf80,0x3ec40000,0x3f6d3f80,0xbf6dbf35,0xbec4bf35,0x3f6d3f35,0x3ec43f35,
0xbf62bf80,0x3ef10000,0x3e953f35,0xbf75bf35,0xbdc9bf0e,0x3f7f3f55,0xbf22be48,0xbf46bf7b,0x3f463ec4,0x3f223f6d,0xbf7fbf6d,0x3dc9bec4,
0x3f753f7b,0xbe953e48,0xbef1bf55,0x3f623f0e,0x3f553f80,0xbf0e0000,0x3f0e0000,0x3f553f80,0xbe483ec4,0xbf7bbf6d,0x3f7b3f6d,0xbe483ec4,
0xbf7bbf35,0xbe48bf35,0x3e483f35,0xbf7bbf35,0xbf0ebf6d,0x3f553ec4,0xbf55bec4,0xbf0ebf6d,0xbf46bf80,0x3f220000,0xbf7fbf35,0xbdc9bf35,
0x3ef1be48,0x3f623f7b,0xbe95bf55,0x3f753f0e,0x3f753f6d,0xbe953ec4,0x3f623ec4,0x3ef13f6d,0xbdc93f0e,0xbf7fbf55,0x3f223f7b,0xbf46be48,
0x3f353f80,0xbf350000,0x3f353f80,0xbf350000,0xbf350000,0xbf35bf80,0xbf350000,0xbf35bf80,0xbf35bf80,0x3f350000,0xbf35bf80,0x3f350000,
0x3f350000,0x3f353f80,0x3f350000,0x3f353f80,0xbf22bf80,0x3f460000,0x3dc9bf35,0x3f7f3f35,0x3f623e48,0x3ef13f7b,0x3f753f55,0xbe953f0e,
0x3e953f6d,0xbf75bec4,0xbef13ec4,0xbf62bf6d,0xbf7fbf0e,0xbdc9bf55,0xbf46bf7b,0x3f22be48,0x3f0e3f80,0xbf550000,0xbf550000,0xbf0ebf80,
0xbf7bbec4,0xbe48bf6d,0xbe48bf6d,0x3f7b3ec4,0x3e48bf35,0x3f7b3f35,0x3f7b3f35,0xbe483f35,0x3f553f6d,0xbf0e3ec4,0xbf0e3ec4,0xbf55bf6d,
0xbef1bf80,0x3f620000,0x3f753f35,0xbe953f35,0x3f7f3f0e,0xbdc93f55,0xbf463e48,0xbf22bf7b,0xbf223ec4,0xbf46bf6d,0xbdc9bf6d,0x3f7f3ec4,
0xbe95bf7b,0x3f753e48,0x3f623f55,0xbef13f0e,0x3ec43f80,0xbf6d0000,0xbec4bf80,0x3f6d0000,0xbf6dbf35,0x3ec4bf35,0x3f6d3f35,0xbec43f35,
0x3f6d0000,0x3ec43f80,0xbf6d0000,0xbec4bf80,0xbec43f35,0xbf6dbf35,0x3ec4bf35,0x3f6d3f35,0xbe95bf80,0x3f750000,0xbef13f35,0xbf62bf35,
0x3f463f55,0xbf223f0e,0xbdc9bf7b,0x3f7f3e48,0xbf7fbec4,0x3dc9bf6d,0x3f223f6d,0xbf463ec4,0x3f62be48,0x3ef13f7b,0xbf75bf0e,0x3e95bf55,
0x3e483f80,0xbf7b0000,0x3f7b0000,0x3e483f80,0xbf0ebf6d,0x3f55bec4,0xbf553ec4,0xbf0ebf6d,0x3f553f35,0xbf0e3f35,0x3f0ebf35,0x3f553f35,
0xbf7bbec4,0x3e48bf6d,0xbe483f6d,0xbf7bbec4,0xbdc9bf80,0x3f7f0000,0xbf46bf35,0x3f22bf35,0x3e953f7b,0xbf753e48,0x3f623f0e,0xbef13f55,
0xbef1bf6d,0x3f62bec4,0xbf75bec4,0x3e95bf6d,0x3f223f55,0xbf463f0e,0x3f7f3e48,0xbdc93f7b,0x3f80,0xbf800000,0x3f80,0xbf800000,
0xbf80,0x3f800000,0xbf80,0x3f800000,0x3f80,0xbf800000,0x3f80,0xbf800000,0xbf80,0x3f800000,0xbf80,0x3f800000,
0x3dc9bf80,0x3f7f0000,0x3f46bf35,0x3f223f35,0xbe953f7b,0xbf75be48,0xbf623f0e,0xbef1bf55,0x3ef1bf6d,0x3f623ec4,0x3f75bec4,0x3e953f6d,
0xbf223f55,0xbf46bf0e,0xbf7f3e48,0xbdc9bf7b,0xbe483f80,0xbf7b0000,0xbf7b0000,0x3e48bf80,0x3f0ebf6d,0x3f553ec4,0x3f553ec4,0xbf0e3f6d,
0xbf553f35,0xbf0ebf35,0xbf0ebf35,0x3f55bf35,0x3f7bbec4,0x3e483f6d,0x3e483f6d,0xbf7b3ec4,0x3e95bf80,0x3f750000,0x3ef13f35,0xbf623f35,
0xbf463f55,0xbf22bf0e,0x3dc9bf7b,0x3f7fbe48,0x3f7fbec4,0x3dc93f6d,0xbf223f6d,0xbf46bec4,0xbf62be48,0x3ef1bf7b,0x3f75bf0e,0x3e953f55,
0xbec43f80,0xbf6d0000,0x3ec4bf80,0x3f6d0000,0x3f6dbf35,0x3ec43f35,0xbf6d3f35,0xbec4bf35,0xbf6d0000,0x3ec4bf80,0x3f6d0000,0xbec43f80,
0x3ec43f35,0xbf6d3f35,0xbec4bf35,0x3f6dbf35,0x3ef1bf80,0x3f620000,0xbf753f35,0xbe95bf35,0xbf7f3f0e,0xbdc9bf55,0x3f463e48,0xbf223f7b,
0x3f223ec4,0xbf463f6d,0x3dc9bf6d,0x3f7fbec4,0x3e95bf7b,0x3f75be48,0xbf623f55,0xbef1bf0e,0xbf0e3f80,0xbf550000,0x3f550000,0xbf0e3f80,
0x3f7bbec4,0xbe483f6d,0x3e48bf6d,0x3f7bbec4,0xbe48bf35,0x3f7bbf35,0xbf7b3f35,0xbe48bf35,0xbf553f6d,0xbf0ebec4,0x3f0e3ec4,0xbf553f6d,
0x3f22bf80,0x3f460000,0xbdc9bf35,0x3f7fbf35,0xbf623e48,0x3ef1bf7b,0xbf753f55,0xbe95bf0e,0xbe953f6d,0xbf753ec4,0x3ef13ec4,0xbf623f6d,
0x3f7fbf0e,0xbdc93f55,0x3f46bf7b,0x3f223e48,0xbf353f80,0xbf350000,0xbf353f80,0xbf350000,0x3f350000,0xbf353f80,0x3f350000,0xbf353f80,
0x3f35bf80,0x3f350000,0x3f35bf80,0x3f350000,0xbf350000,0x3f35bf80,0xbf350000,0x3f35bf80,0x3f46bf80,0x3f220000,0x3f7fbf35,0xbdc93f35,
0xbef1be48,0x3f62bf7b,0x3e95bf55,0x3f75bf0e,0xbf753f6d,0xbe95bec4,0xbf623ec4,0x3ef1bf6d,0x3dc93f0e,0xbf7f3f55,0xbf223f7b,0xbf463e48,
0xbf553f80,0xbf0e0000,0xbf0e0000,0x3f55bf80,0x3e483ec4,0xbf7b3f6d,0xbf7b3f6d,0xbe48bec4,0x3f7bbf35,0xbe483f35,0xbe483f35,0xbf7b3f35,
0x3f0ebf6d,0x3f55bec4,0x3f55bec4,0xbf0e3f6d,0x3f62bf80,0x3ef10000,0xbe953f35,0xbf753f35,0x3dc9bf0e,0x3f7fbf55,0x3f22be48,0xbf463f7b,
0xbf463ec4,0x3f22bf6d,0x3f7fbf6d,0x3dc93ec4,0xbf753f7b,0xbe95be48,0x3ef1bf55,0x3f62bf0e,0xbf6d3f80,0xbec40000,0x3f6dbf80,0x3ec40000,
0xbec43f35,0xbf6d3f35,0x3ec4bf35,0x3f6dbf35,0x3ec40000,0xbf6d3f80,0xbec40000,0x3f6dbf80,0x3f6dbf35,0xbec43f35,0xbf6d3f35,0x3ec4bf35,
0x3f75bf80,0x3e950000,0xbf623f35,0x3ef1bf35,0x3f22bf55,0x3f46bf0e,0xbf7f3f7b,0xbdc9be48,0x3dc9bec4,0x3f7fbf6d,0xbf463f6d,0xbf223ec4,
0xbef13e48,0x3f62bf7b,0xbe953f0e,0xbf753f55,0xbf7b3f80,0xbe480000,0x3e480000,0xbf7b3f80,0xbf553f6d,0xbf0e3ec4,0x3f0ebec4,0xbf553f6d,
0xbf0e3f35,0xbf553f35,0x3f55bf35,0xbf0e3f35,0xbe483ec4,0xbf7b3f6d,0x3f7bbf6d,0xbe483ec4,0x3f7fbf80,0x3dc90000,0x3f22bf35,0x3f46bf35,
0x3f75bf7b,0x3e95be48,0x3ef1bf0e,0x3f62bf55,0x3f62bf6d,0x3ef1bec4,0x3e95bec4,0x3f75bf6d,0x3f46bf55,0x3f22bf0e,0x3dc9be48,0x3f7fbf7b,
0x3f803f80,0xbf803f80,0x3f803f80,0xbf803f80,0x3f803f80,0xbf803f80,0x3f803f80,0xbf803f80,0x3f803f80,0xbf803f80,0x3f803f80,0xbf803f80,
0x3f803f80,0xbf803f80,0x3f803f80,0xbf803f80,0x3dc90000,0x3f7f3f80,0x3f463f35,0x3f223f35,0x3e953e48,0x3f753f7b,0x3f623f55,0x3ef13f0e,
0x3ef13ec4,0x3f623f6d,0x3f753f6d,0x3e953ec4,0x3f223f0e,0x3f463f55,0x3f7f3f7b,0x3dc93e48,0xbf7bbf80,0x3e480000,0x3e480000,0x3f7b3f80,
0xbf55bf6d,0x3f0e3ec4,0x3f0e3ec4,0x3f553f6d,0xbf0ebf35,0x3f553f35,0x3f553f35,0x3f0e3f35,0xbe48bec4,0x3f7b3f6d,0x3f7b3f6d,0x3e483ec4,
0xbe950000,0xbf75bf80,0xbef1bf35,0x3f623f35,0xbf46bf0e,0xbf22bf55,0x3dc9be48,0x3f7f3f7b,0xbf7fbf6d,0xbdc9bec4,0x3f223ec4,0x3f463f6d,
0xbf62bf7b,0x3ef13e48,0x3f753f55,0x3e953f0e,0x3f6d3f80,0xbec40000,0xbf6dbf80,0x3ec40000,0x3ec43f35,0xbf6dbf35,0xbec4bf35,0x3f6d3f35,
0xbec40000,0xbf6dbf80,0x3ec40000,0x3f6d3f80,0xbf6dbf35,0xbec4bf35,0x3f6d3f35,0x3ec43f35,0x3ef10000,0x3f623f80,0xbf75bf35,0xbe95bf35,
0x3f7f3f55,0x3dc93f0e,0xbf46bf7b,0x3f223e48,0x3f223f6d,0xbf46bec4,0x3dc9bec4,0x3f7f3f6d,0xbe953e48,0xbf75bf7b,0x3f623f0e,0x3ef13f55,
0xbf55bf80,0x3f0e0000,0xbf0e0000,0xbf55bf80,0x3e48bec4,0x3f7b3f6d,0xbf7bbf6d,0x3e48bec4,0x3f7b3f35,0x3e483f35,0xbe48bf35,0x3f7b3f35,
0x3f0e3f6d,0xbf55bec4,0x3f553ec4,0x3f0e3f6d,0xbf220000,0xbf46bf80,0x3dc93f35,0xbf7fbf35,0xbf62bf7b,0x3ef1be48,0xbf75bf0e,0xbe95bf55,
0x3e95bec4,0x3f753f6d,0xbef1bf6d,0x3f623ec4,0x3f7f3f55,0xbdc93f0e,0x3f463e48,0x3f223f7b,0x3f353f80,0xbf350000,0x3f353f80,0xbf350000,
0xbf350000,0xbf35bf80,0xbf350000,0xbf35bf80,0xbf35bf80,0x3f350000,0xbf35bf80,0x3f350000,0x3f350000,0x3f353f80,0x3f350000,0x3f353f80,
0x3f460000,0x3f223f80,0x3f7f3f35,0xbdc93f35,0x3ef13f7b,0xbf62be48,0xbe953f0e,0xbf75bf55,0xbf75bec4,0xbe95bf6d,0xbf62bf6d,0x3ef1bec4,
0xbdc9bf55,0x3f7f3f0e,0x3f22be48,0x3f463f7b,0xbf0ebf80,0x3f550000,0x3f550000,0x3f0e3f80,0x3f7b3ec4,0x3e483f6d,0x3e483f6d,0xbf7bbec4,
0xbe483f35,0xbf7bbf35,0xbf7bbf35,0x3e48bf35,0xbf55bf6d,0x3f0ebec4,0x3f0ebec4,0x3f553f6d,0xbf620000,0xbef1bf80,0x3e95bf35,0x3f753f35,
0x3dc9bf55,0x3f7f3f0e,0x3f223f7b,0xbf463e48,0x3f463f6d,0xbf223ec4,0xbf7fbec4,0xbdc9bf6d,0xbf75be48,0xbe95bf7b,0x3ef1bf0e,0x3f623f55,
0x3ec43f80,0xbf6d0000,0xbec4bf80,0x3f6d0000,0xbf6dbf35,0x3ec4bf35,0x3f6d3f35,0xbec43f35,0x3f6d0000,0x3ec43f80,0xbf6d0000,0xbec4bf80,
0xbec43f35,0xbf6dbf35,0x3ec4bf35,0x3f6d3f35,0x3f750000,0x3e953f80,0xbf62bf35,0x3ef1bf35,0xbf223f0e,0xbf46bf55,0x3f7f3e48,0x3dc93f7b,
0x3dc9bf6d,0x3f7f3ec4,0xbf463ec4,0xbf22bf6d,0x3ef13f7b,0xbf623e48,0x3e95bf55,0x3f753f0e,0xbe48bf80,0x3f7b0000,0xbf7b0000,0xbe48bf80,
0x3f0e3f6d,0xbf553ec4,0x3f55bec4,0x3f0e3f6d,0xbf55bf35,0x3f0ebf35,0xbf0e3f35,0xbf55bf35,0x3f7b3ec4,0xbe483f6d,0x3e48bf6d,0x3f7b3ec4,
0xbf7f0000,0xbdc9bf80,0xbf223f35,0xbf46bf35,0x3f75be48,0x3e953f7b,0x3ef1bf55,0x3f623f0e,0xbf623ec4,0xbef1bf6d,0xbe953f6d,0xbf75bec4,
0x3f46bf0e,0x3f223f55,0x3dc9bf7b,0x3f7f3e48,0x3f80,0xbf800000,0x3f80,0xbf800000,0xbf80,0x3f800000,0xbf80,0x3f800000,
0x3f80,0xbf800000,0x3f80,0xbf800000,0xbf80,0x3f800000,0xbf80,0x3f800000,0x3f7f0000,0xbdc93f80,0x3f223f35,0xbf463f35,
0xbf75be48,0x3e95bf7b,0xbef1bf55,0x3f62bf0e,0x3f623ec4,0xbef13f6d,0x3e953f6d,0xbf753ec4,0xbf46bf0e,0x3f22bf55,0xbdc9bf7b,0x3f7fbe48,
0x3e48bf80,0x3f7b0000,0x3f7b0000,0xbe483f80,0xbf0e3f6d,0xbf55bec4,0xbf55bec4,0x3f0ebf6d,0x3f55bf35,0x3f0e3f35,0x3f0e3f35,0xbf553f35,
0xbf7b3ec4,0xbe48bf6d,0xbe48bf6d,0x3f7bbec4,0xbf750000,0x3e95bf80,0x3f62bf35,0x3ef13f35,0x3f223f0e,0xbf463f55,0xbf7f3e48,0x3dc9bf7b,
0xbdc9bf6d,0x3f7fbec4,0x3f463ec4,0xbf223f6d,0xbef13f7b,0xbf62be48,0xbe95bf55,0x3f75bf0e,0xbec43f80,0xbf6d0000,0x3ec4bf80,0x3f6d0000,
0x3f6dbf35,0x3ec43f35,0xbf6d3f35,0xbec4bf35,0xbf6d0000,0x3ec4bf80,0x3f6d0000,0xbec43f80,0x3ec43f35,0xbf6d3f35,0xbec4bf35,0x3f6dbf35,
0x3f620000,0xbef13f80,0xbe95bf35,0x3f75bf35,0xbdc9bf55,0x3f7fbf0e,0xbf223f7b,0xbf46be48,0xbf463f6d,0xbf22bec4,0x3f7fbec4,0xbdc93f6d,
0x3f75be48,0xbe953f7b,0xbef1bf0e,0x3f62bf55,0x3f0ebf80,0x3f550000,0xbf550000,0x3f0ebf80,0xbf7b3ec4,0x3e48bf6d,0xbe483f6d,0xbf7b3ec4,
0x3e483f35,0xbf7b3f35,0x3f7bbf35,0x3e483f35,0x3f55bf6d,0x3f0e3ec4,0xbf0ebec4,0x3f55bf6d,0xbf460000,0x3f22bf80,0xbf7f3f35,0xbdc9bf35,
0xbef13f7b,0xbf623e48,0x3e953f0e,0xbf753f55,0x3f75bec4,0xbe953f6d,0x3f62bf6d,0x3ef13ec4,0x3dc9bf55,0x3f7fbf0e,0xbf22be48,0x3f46bf7b,
0xbf353f80,0xbf350000,0xbf353f80,0xbf350000,0x3f350000,0xbf353f80,0x3f350000,0xbf353f80,0x3f35bf80,0x3f350000,0x3f35bf80,0x3f350000,
0xbf350000,0x3f35bf80,0xbf350000,0x3f35bf80,0x3f220000,0xbf463f80,0xbdc93f35,0xbf7f3f35,0x3f62bf7b,0x3ef13e48,0x3f75bf0e,0xbe953f55,
0xbe95bec4,0x3f75bf6d,0x3ef1bf6d,0x3f62bec4,0xbf7f3f55,0xbdc9bf0e,0xbf463e48,0x3f22bf7b,0x3f55bf80,0x3f0e0000,0x3f0e0000,0xbf553f80,
0xbe48bec4,0x3f7bbf6d,0x3f7bbf6d,0x3e483ec4,0xbf7b3f35,0x3e48bf35,0x3e48bf35,0x3f7bbf35,0xbf0e3f6d,0xbf553ec4,0xbf553ec4,0x3f0ebf6d,
0xbef10000,0x3f62bf80,0x3f75bf35,0xbe953f35,0xbf7f3f55,0x3dc9bf0e,0x3f46bf7b,0x3f22be48,0xbf223f6d,0xbf463ec4,0xbdc9bec4,0x3f7fbf6d,
0x3e953e48,0xbf753f7b,0xbf623f0e,0x3ef1bf55,0xbf6d3f80,0xbec40000,0x3f6dbf80,0x3ec40000,0xbec43f35,0xbf6d3f35,0x3ec4bf35,0x3f6dbf35,
0x3ec40000,0xbf6d3f80,0xbec40000,0x3f6dbf80,0x3f6dbf35,0xbec43f35,0xbf6d3f35,0x3ec4bf35,0x3e950000,0xbf753f80,0x3ef1bf35,0x3f62bf35,
0x3f46bf0e,0xbf223f55,0xbdc9be48,0x3f7fbf7b,0x3f7fbf6d,0xbdc93ec4,0xbf223ec4,0x3f46bf6d,0x3f62bf7b,0x3ef1be48,0xbf753f55,0x3e95bf0e,
0x3f7bbf80,0x3e480000,0xbe480000,0x3f7bbf80,0x3f55bf6d,0x3f0ebec4,0xbf0e3ec4,0x3f55bf6d,0x3f0ebf35,0x3f55bf35,0xbf553f35,0x3f0ebf35,
0x3e48bec4,0x3f7bbf6d,0xbf7b3f6d,0x3e48bec4,0xbdc90000,0x3f7fbf80,0xbf463f35,0x3f22bf35,0xbe953e48,0x3f75bf7b,0xbf623f55,0x3ef1bf0e,
0xbef13ec4,0x3f62bf6d,0xbf753f6d,0x3e95bec4,0xbf223f0e,0x3f46bf55,0xbf7f3f7b,0x3dc9be48,0x40003f80,0x3fb53f80,0x3f80,0xbfb53f80,
0x40004000,0xbfb50000,0x0,0xbfb5c000,0x40004000,0xbfb5c000,0x0,0x3fb50000,0x40004000,0x3fb50000,0x0,0x3fb54000,
0x3fff3f80,0x3fa23f80,0xbe49bf80,0xbfc6bf80,0x3ff53ffb,0xbfe2bec8,0xbf15bec8,0xbf71bffb,0x3fe23fed,0xbf15bfed,0xbf71bf44,0x3ff53f44,
0x3fc63fd5,0x3fff3f8e,0xbfa2bf8e,0x3e493fd5,0x3ffb3f80,0x3f8e3f80,0xbec83f80,0xbfd53f80,0x3fd53fed,0xbffbbf44,0xbf8ebf44,0xbec8bfed,
0x3f8e3fb5,0x3ec8bfb5,0xbfd5bfb5,0x3ffb3fb5,0x3ec83f44,0x3fd53fed,0xbffbbfed,0xbf8e3f44,0x3ff53f80,0x3f713f80,0xbf15bf80,0xbfe2bf80,
0x3fa23fd5,0xbfffbf8e,0xbfc6bf8e,0x3e49bfd5,0x3e493f44,0x3fa2bf44,0xbfffbfed,0x3fc63fed,0xbf71bec8,0x3f153ffb,0xbfe2bffb,0xbff5bec8,
0x3fed3f80,0x3f443f80,0xbf443f80,0xbfed3f80,0x3f443fb5,0xbfedbfb5,0xbfedbfb5,0x3f44bfb5,0xbf440000,0x3fed0000,0xbfedc000,0x3f444000,
0xbfedbfb5,0xbf443fb5,0xbf44bfb5,0xbfedbfb5,0x3fe23f80,0x3f153f80,0xbf71bf80,0xbff5bf80,0x3e493f8e,0xbfc6bfd5,0xbfffbfd5,0x3fa2bf8e,
0xbfc6bf44,0x3fff3f44,0xbfa2bfed,0xbe493fed,0xbff5bffb,0xbfe23ec8,0x3f15bec8,0xbf71bffb,0x3fd53f80,0x3ec83f80,0xbf8e3f80,0xbffb3f80,
0xbec83f44,0xbf8ebfed,0xbffbbfed,0x3fd5bf44,0xbffbbfb5,0x3fd53fb5,0xbec8bfb5,0xbf8e3fb5,0xbf8ebfed,0xbffbbf44,0x3fd53f44,0x3ec8bfed,
0x3fc63f80,0x3e493f80,0xbfa2bf80,0xbfffbf80,0xbf713ec8,0xbf15bffb,0xbfe2bffb,0x3ff5bec8,0xbff5bfed,0x3f713fed,0x3f15bf44,0xbfe23f44,
0x3e49bf8e,0xbfa2bfd5,0x3fff3fd5,0x3fc6bf8e,0x3f80,0xbfb53f80,0xc0003f80,0xbfb53f80,0xc000,0x3fb50000,0x40000000,0xbfb54000,
0x4000,0x3fb5c000,0xc0000000,0x3fb50000,0xc000,0xbfb50000,0x40000000,0x3fb5c000,0xbe493f80,0xbfc63f80,0xbfffbf80,0xbfa2bf80,
0x3f15bffb,0x3f713ec8,0x3ff53ec8,0xbfe23ffb,0xbf713fed,0x3ff5bfed,0xbfe2bf44,0x3f153f44,0x3fa2bfd5,0xbe49bf8e,0x3fc63f8e,0x3fffbfd5,
0xbec83f80,0xbfd53f80,0xbffb3f80,0xbf8e3f80,0x3f8ebfed,0x3ec83f44,0x3fd53f44,0xbffb3fed,0xbfd53fb5,0x3ffbbfb5,0xbf8ebfb5,0xbec83fb5,
0x3ffbbf44,0x3f8ebfed,0x3ec83fed,0x3fd5bf44,0xbf153f80,0xbfe23f80,0xbff5bf80,0xbf71bf80,0x3fc6bfd5,0xbe493f8e,0x3fa23f8e,0xbfff3fd5,
0xbfff3f44,0x3fc6bf44,0xbe49bfed,0xbfa23fed,0x3fe23ec8,0x3ff5bffb,0xbf713ffb,0x3f153ec8,0xbf443f80,0xbfed3f80,0xbfed3f80,0xbf443f80,
0x3fedbfb5,0xbf443fb5,0x3f443fb5,0xbfed3fb5,0xbfed0000,0x3f440000,0x3f44c000,0xbfed4000,0x3f443fb5,0x3fedbfb5,0xbfed3fb5,0xbf443fb5,
0xbf713f80,0xbff53f80,0xbfe2bf80,0xbf15bf80,0x3fffbf8e,0xbfa23fd5,0x3e493fd5,0xbfc63f8e,0xbfa2bf44,0xbe493f44,0x3fc6bfed,0xbfff3fed,
0xbf153ffb,0x3f71bec8,0xbff53ec8,0xbfe23ffb,0xbf8e3f80,0xbffb3f80,0xbfd53f80,0xbec83f80,0x3ffbbf44,0xbfd53fed,0xbec83fed,0xbf8e3f44,
0xbec8bfb5,0xbf8e3fb5,0x3ffbbfb5,0xbfd53fb5,0xbfd53fed,0xbec83f44,0xbf8ebf44,0xbffb3fed,0xbfa23f80,0xbfff3f80,0xbfc6bf80,0xbe49bf80,
0x3fe2bec8,0xbff53ffb,0xbf713ffb,0xbf153ec8,0x3f15bfed,0xbfe23fed,0x3ff5bf44,0xbf713f44,0xbfff3f8e,0xbfc63fd5,0x3e49bfd5,0xbfa23f8e,
0xc0003f80,0xbfb53f80,0x3f80,0x3fb53f80,0xc0004000,0x3fb50000,0x0,0x3fb5c000,0xc0004000,0x3fb5c000,0x0,0xbfb50000,
0xc0004000,0xbfb50000,0x0,0xbfb54000,0xbfff3f80,0xbfa23f80,0x3e49bf80,0x3fc6bf80,0xbff53ffb,0x3fe2bec8,0x3f15bec8,0x3f71bffb,
0xbfe23fed,0x3f15bfed,0x3f71bf44,0xbff53f44,0xbfc63fd5,0xbfff3f8e,0x3fa2bf8e,0xbe493fd5,0xbffb3f80,0xbf8e3f80,0x3ec83f80,0x3fd53f80,
0xbfd53fed,0x3ffbbf44,0x3f8ebf44,0x3ec8bfed,0xbf8e3fb5,0xbec8bfb5,0x3fd5bfb5,0xbffb3fb5,0xbec83f44,0xbfd53fed,0x3ffbbfed,0x3f8e3f44,
0xbff53f80,0xbf713f80,0x3f15bf80,0x3fe2bf80,0xbfa23fd5,0x3fffbf8e,0x3fc6bf8e,0xbe49bfd5,0xbe493f44,0xbfa2bf44,0x3fffbfed,0xbfc63fed,
0x3f71bec8,0xbf153ffb,0x3fe2bffb,0x3ff5bec8,0xbfed3f80,0xbf443f80,0x3f443f80,0x3fed3f80,0xbf443fb5,0x3fedbfb5,0x3fedbfb5,0xbf44bfb5,
0x3f440000,0xbfed0000,0x3fedc000,0xbf444000,0x3fedbfb5,0x3f443fb5,0x3f44bfb5,0x3fedbfb5,0xbfe23f80,0xbf153f80,0x3f71bf80,0x3ff5bf80,
0xbe493f8e,0x3fc6bfd5,0x3fffbfd5,0xbfa2bf8e,0x3fc6bf44,0xbfff3f44,0x3fa2bfed,0x3e493fed,0x3ff5bffb,0x3fe23ec8,0xbf15bec8,0x3f71bffb,
0xbfd53f80,0xbec83f80,0x3f8e3f80,0x3ffb3f80,0x3ec83f44,0x3f8ebfed,0x3ffbbfed,0xbfd5bf44,0x3ffbbfb5,0xbfd53fb5,0x3ec8bfb5,0x3f8e3fb5,
0x3f8ebfed,0x3ffbbf44,0xbfd53f44,0xbec8bfed,0xbfc63f80,0xbe493f80,0x3fa2bf80,0x3fffbf80,0x3f713ec8,0x3f15bffb,0x3fe2bffb,0xbff5bec8,
0x3ff5bfed,0xbf713fed,0xbf15bf44,0x3fe23f44,0xbe49bf8e,0x3fa2bfd5,0xbfff3fd5,0xbfc6bf8e,0x3f80,0x3fb53f80,0x40003f80,0x3fb53f80,
0xc000,0xbfb50000,0xc0000000,0x3fb54000,0x4000,0xbfb5c000,0x40000000,0xbfb50000,0xc000,0x3fb50000,0xc0000000,0xbfb5c000,
0x3e493f80,0x3fc63f80,0x3fffbf80,0x3fa2bf80,0xbf15bffb,0xbf713ec8,0xbff53ec8,0x3fe23ffb,0x3f713fed,0xbff5bfed,0x3fe2bf44,0xbf153f44,
0xbfa2bfd5,0x3e49bf8e,0xbfc63f8e,0xbfffbfd5,0x3ec83f80,0x3fd53f80,0x3ffb3f80,0x3f8e3f80,0xbf8ebfed,0xbec83f44,0xbfd53f44,0x3ffb3fed,
0x3fd53fb5,0xbffbbfb5,0x3f8ebfb5,0x3ec83fb5,0xbffbbf44,0xbf8ebfed,0xbec83fed,0xbfd5bf44,0x3f153f80,0x3fe23f80,0x3ff5bf80,0x3f71bf80,
0xbfc6bfd5,0x3e493f8e,0xbfa23f8e,0x3fff3fd5,0x3fff3f44,0xbfc6bf44,0x3e49bfed,0x3fa23fed,0xbfe23ec8,0xbff5bffb,0x3f713ffb,0xbf153ec8,
0x3f443f80,0x3fed3f80,0x3fed3f80,0x3f443f80,0xbfedbfb5,0x3f443fb5,0xbf443fb5,0x3fed3fb5,0x3fed0000,0xbf440000,0xbf44c000,0x3fed4000,
0xbf443fb5,0xbfedbfb5,0x3fed3fb5,0x3f443fb5,0x3f713f80,0x3ff53f80,0x3fe2bf80,0x3f15bf80,0xbfffbf8e,0x3fa23fd5,0xbe493fd5,0x3fc63f8e,
0x3fa2bf44,0x3e493f44,0xbfc6bfed,0x3fff3fed,0x3f153ffb,0xbf71bec8,0x3ff53ec8,0x3fe23ffb,0x3f8e3f80,0x3ffb3f80,0x3fd53f80,0x3ec83f80,
0xbffbbf44,0x3fd53fed,0x3ec83fed,0x3f8e3f44,0x3ec8bfb5,0x3f8e3fb5,0xbffbbfb5,0x3fd53fb5,0x3fd53fed,0x3ec83f44,0x3f8ebf44,0x3ffb3fed,
0x3fa23f80,0x3fff3f80,0x3fc6bf80,0x3e49bf80,0xbfe2bec8,0x3ff53ffb,0x3f713ffb,0x3f153ec8,0xbf15bfed,0x3fe23fed,0xbff5bf44,0x3f713f44,
0x3fff3f8e,0x3fc63fd5,0xbe49bfd5,0x3fa23f8e,0x40004000,0x3fb54000,0x0,0xbfb50000,0x40004000,0xbfb50000,0x0,0xbfb5c000,
0x40004000,0xbfb5c000,0x0,0x3fb50000,0x40004000,0x3fb50000,0x0,0x3fb54000,0x3fa23fb5,0xbe493fb5,0xbfc6bfb5,0xbfffbfb5,
0x3f713f8e,0xbff5bfd5,0xbfe2bfd5,0x3f15bf8e,0x3f153f44,0x3f71bf44,0xbff5bfed,0x3fe23fed,0x3e493ec8,0x3fc63ffb,0xbfffbffb,0xbfa23ec8,
0xbec80000,0xbfd50000,0xbffbc000,0xbf8ec000,0xbf8ebf44,0xbec8bfed,0xbfd5bfed,0x3ffb3f44,0xbfd5bfb5,0x3ffb3fb5,0xbf8ebfb5,0xbec83fb5,
0xbffbbfed,0xbf8e3f44,0xbec8bf44,0xbfd5bfed,0xbfe2bfb5,0xbff5bfb5,0xbf71bfb5,0x3f15bfb5,0xbfffbffb,0x3fc6bec8,0x3e49bec8,0x3fa23ffb,
0xbfc6bfed,0x3e493fed,0x3fa23f44,0xbfffbf44,0xbf15bf8e,0xbfe2bfd5,0x3ff53fd5,0x3f71bf8e,0xbfedc000,0xbf44c000,0x3f440000,0x3fed0000,
0xbf44bfb5,0x3fed3fb5,0x3fed3fb5,0xbf443fb5,0x3f440000,0xbfed0000,0x3fed4000,0xbf44c000,0x3fed3fb5,0x3f44bfb5,0x3f443fb5,0x3fed3fb5,
0xbf15bfb5,0x3f71bfb5,0x3ff53fb5,0x3fe23fb5,0x3fa23ec8,0x3e493ffb,0x3fc63ffb,0xbfffbec8,0x3fff3fed,0xbfa2bfed,0xbe493f44,0x3fc6bf44,
0x3f713fd5,0x3ff53f8e,0xbfe2bf8e,0xbf153fd5,0x3f8e0000,0x3ffb0000,0x3fd54000,0x3ec84000,0x3ffb3fed,0xbfd53f44,0xbec83f44,0xbf8ebfed,
0x3ec83fb5,0x3f8ebfb5,0xbffbbfb5,0x3fd53fb5,0xbfd5bf44,0xbec83fed,0xbf8ebfed,0xbffbbf44,0x3fff3fb5,0x3fc63fb5,0x3e493fb5,0xbfa23fb5,
0x3f153fd5,0xbfe2bf8e,0xbff5bf8e,0x3f71bfd5,0xbfe2bf44,0x3ff53f44,0xbf71bfed,0xbf153fed,0xbfa2bffb,0xbfffbec8,0x3fc63ec8,0x3e49bffb,
0x4000,0xbfb54000,0xc0000000,0xbfb50000,0xc000,0x3fb50000,0x40000000,0xbfb54000,0x4000,0x3fb5c000,0xc0000000,0x3fb50000,
0xc000,0xbfb50000,0x40000000,0x3fb5c000,0xbfc63fb5,0xbfff3fb5,0xbfa2bfb5,0x3e49bfb5,0x3fe2bf8e,0xbf153fd5,0x3f713fd5,0xbff53f8e,
0xbff53f44,0x3fe2bf44,0xbf15bfed,0xbf713fed,0x3fffbec8,0x3fa2bffb,0x3e493ffb,0x3fc6bec8,0xbffb0000,0xbf8e0000,0x3ec8c000,0x3fd5c000,
0x3fd53f44,0xbffb3fed,0xbf8e3fed,0xbec8bf44,0xbf8ebfb5,0xbec83fb5,0x3fd5bfb5,0xbffb3fb5,0x3ec83fed,0x3fd5bf44,0xbffb3f44,0xbf8e3fed,
0xbf71bfb5,0x3f15bfb5,0x3fe2bfb5,0x3ff5bfb5,0xbe493ffb,0xbfa23ec8,0xbfff3ec8,0x3fc6bffb,0x3fa2bfed,0xbfff3fed,0x3fc63f44,0xbe49bf44,
0xbff53f8e,0xbf713fd5,0xbf15bfd5,0xbfe23f8e,0x3f44c000,0x3fedc000,0x3fed0000,0x3f440000,0xbfed3fb5,0x3f44bfb5,0xbf44bfb5,0x3fedbfb5,
0x3fed0000,0xbf440000,0xbf444000,0x3fedc000,0xbf44bfb5,0xbfed3fb5,0x3fedbfb5,0x3f44bfb5,0x3ff5bfb5,0x3fe2bfb5,0x3f153fb5,0xbf713fb5,
0xbfc6bec8,0x3fffbffb,0x3fa2bffb,0x3e493ec8,0xbe493fed,0x3fc6bfed,0xbfff3f44,0x3fa2bf44,0x3fe2bfd5,0x3f15bf8e,0x3f713f8e,0x3ff5bfd5,
0x3fd50000,0x3ec80000,0xbf8e4000,0xbffb4000,0x3ec8bfed,0x3f8ebf44,0x3ffbbf44,0xbfd53fed,0xbffb3fb5,0x3fd5bfb5,0xbec8bfb5,0xbf8e3fb5,
0x3f8e3f44,0x3ffbbfed,0xbfd53fed,0xbec83f44,0x3e493fb5,0xbfa23fb5,0xbfff3fb5,0xbfc63fb5,0x3ff5bfd5,0xbf713f8e,0x3f153f8e,0xbfe23fd5,
0xbf71bf44,0xbf153f44,0x3fe2bfed,0xbff53fed,0xbfc63ffb,0xbe493ec8,0xbfa2bec8,0xbfff3ffb,0xc0004000,0xbfb54000,0x0,0x3fb50000,
0xc0004000,0x3fb50000,0x0,0x3fb5c000,0xc0004000,0x3fb5c000,0x0,0xbfb50000,0xc0004000,0xbfb50000,0x0,0xbfb54000,
0xbfa23fb5,0x3e493fb5,0x3fc6bfb5,0x3fffbfb5,0xbf713f8e,0x3ff5bfd5,0x3fe2bfd5,0xbf15bf8e,0xbf153f44,0xbf71bf44,0x3ff5bfed,0xbfe23fed,
0xbe493ec8,0xbfc63ffb,0x3fffbffb,0x3fa23ec8,0x3ec80000,0x3fd50000,0x3ffbc000,0x3f8ec000,0x3f8ebf44,0x3ec8bfed,0x3fd5bfed,0xbffb3f44,
0x3fd5bfb5,0xbffb3fb5,0x3f8ebfb5,0x3ec83fb5,0x3ffbbfed,0x3f8e3f44,0x3ec8bf44,0x3fd5bfed,0x3fe2bfb5,0x3ff5bfb5,0x3f71bfb5,0xbf15bfb5,
0x3fffbffb,0xbfc6bec8,0xbe49bec8,0xbfa23ffb,0x3fc6bfed,0xbe493fed,0xbfa23f44,0x3fffbf44,0x3f15bf8e,0x3fe2bfd5,0xbff53fd5,0xbf71bf8e,
0x3fedc000,0x3f44c000,0xbf440000,0xbfed0000,0x3f44bfb5,0xbfed3fb5,0xbfed3fb5,0x3f443fb5,0xbf440000,0x3fed0000,0xbfed4000,0x3f44c000,
0xbfed3fb5,0xbf44bfb5,0xbf443fb5,0xbfed3fb5,0x3f15bfb5,0xbf71bfb5,0xbff53fb5,0xbfe23fb5,0xbfa23ec8,0xbe493ffb,0xbfc63ffb,0x3fffbec8,
0xbfff3fed,0x3fa2bfed,0x3e493f44,0xbfc6bf44,0xbf713fd5,0xbff53f8e,0x3fe2bf8e,0x3f153fd5,0xbf8e0000,0xbffb0000,0xbfd54000,0xbec84000,
0xbffb3fed,0x3fd53f44,0x3ec83f44,0x3f8ebfed,0xbec83fb5,0xbf8ebfb5,0x3ffbbfb5,0xbfd53fb5,0x3fd5bf44,0x3ec83fed,0x3f8ebfed,0x3ffbbf44,
0xbfff3fb5,0xbfc63fb5,0xbe493fb5,0x3fa23fb5,0xbf153fd5,0x3fe2bf8e,0x3ff5bf8e,0xbf71bfd5,0x3fe2bf44,0xbff53f44,0x3f71bfed,0x3f153fed,
0x3fa2bffb,0x3fffbec8,0xbfc63ec8,0xbe49bffb,0x4000,0x3fb54000,0x40000000,0x3fb50000,0xc000,0xbfb50000,0xc0000000,0x3fb54000,
0x4000,0xbfb5c000,0x40000000,0xbfb50000,0xc000,0x3fb50000,0xc0000000,0xbfb5c000,0x3fc63fb5,0x3fff3fb5,0x3fa2bfb5,0xbe49bfb5,
0xbfe2bf8e,0x3f153fd5,0xbf713fd5,0x3ff53f8e,0x3ff53f44,0xbfe2bf44,0x3f15bfed,0x3f713fed,0xbfffbec8,0xbfa2bffb,0xbe493ffb,0xbfc6bec8,
0x3ffb0000,0x3f8e0000,0xbec8c000,0xbfd5c000,0xbfd53f44,0x3ffb3fed,0x3f8e3fed,0x3ec8bf44,0x3f8ebfb5,0x3ec83fb5,0xbfd5bfb5,0x3ffb3fb5,
0xbec83fed,0xbfd5bf44,0x3ffb3f44,0x3f8e3fed,0x3f71bfb5,0xbf15bfb5,0xbfe2bfb5,0xbff5bfb5,0x3e493ffb,0x3fa23ec8,0x3fff3ec8,0xbfc6bffb,
0xbfa2bfed,0x3fff3fed,0xbfc63f44,0x3e49bf44,0x3ff53f8e,0x3f713fd5,0x3f15bfd5,0x3fe23f8e,0xbf44c000,0xbfedc000,0xbfed0000,0xbf440000,
0x3fed3fb5,0xbf44bfb5,0x3f44bfb5,0xbfedbfb5,0xbfed0000,0x3f440000,0x3f444000,0xbfedc000,0x3f44bfb5,0x3fed3fb5,0xbfedbfb5,0xbf44bfb5,
0xbff5bfb5,0xbfe2bfb5,0xbf153fb5,0x3f713fb5,0x3fc6bec8,0xbfffbffb,0xbfa2bffb,0xbe493ec8,0x3e493fed,0xbfc6bfed,0x3fff3f44,0xbfa2bf44,
0xbfe2bfd5,0xbf15bf8e,0xbf713f8e,0xbff5bfd5,0xbfd50000,0xbec80000,0x3f8e4000,0x3ffb4000,0xbec8bfed,0xbf8ebf44,0xbffbbf44,0x3fd53fed,
0x3ffb3fb5,0xbfd5bfb5,0x3ec8bfb5,0x3f8e3fb5,0xbf8e3f44,0xbffbbfed,0x3fd53fed,0x3ec83f44,0xbe493fb5,0x3fa23fb5,0x3fff3fb5,0x3fc63fb5,
0xbff5bfd5,0x3f713f8e,0xbf153f8e,0x3fe23fd5,0x3f71bf44,0x3f153f44,0xbfe2bfed,0x3ff53fed,0x3fc63ffb,0x3e493ec8,0x3fa2bec8,0x3fff3ffb,
0x40004000,0x3fb54000,0x0,0xbfb50000,0x40004000,0xbfb50000,0x0,0xbfb5c000,0x40004000,0xbfb5c000,0x0,0x3fb50000,
0x40004000,0x3fb50000,0x0,0x3fb54000,0xbe490000,0xbfc60000,0xbfffc000,0xbfa2c000,0xbf15bec8,0xbf71bffb,0xbff5bffb,0x3fe23ec8,
0xbf71bf44,0x3ff53f44,0xbfe2bfed,0x3f153fed,0xbfa2bf8e,0x3e493fd5,0xbfc6bfd5,0xbfffbf8e,0xbffbc000,0xbf8ec000,0x3ec80000,0x3fd50000,
0xbfd5bfed,0x3ffb3f44,0x3f8e3f44,0x3ec83fed,0xbf8ebfb5,0xbec83fb5,0x3fd53fb5,0xbffbbfb5,0xbec8bf44,0xbfd5bfed,0x3ffb3fed,0x3f8ebf44,
0x3f150000,0x3fe20000,0x3ff54000,0x3f714000,0x3fc63f8e,0xbe493fd5,0x3fa23fd5,0xbfffbf8e,0x3fff3fed,0xbfc6bfed,0x3e493f44,0x3fa2bf44,
0x3fe23ffb,0x3ff53ec8,0xbf71bec8,0x3f153ffb,0x3fed4000,0x3f444000,0xbf440000,0xbfed0000,0x3f443fb5,0xbfedbfb5,0xbfedbfb5,0x3f44bfb5,
0xbf440000,0x3fed0000,0xbfedc000,0x3f444000,0xbfedbfb5,0xbf443fb5,0xbf44bfb5,0xbfedbfb5,0xbf710000,0xbff50000,0xbfe2c000,0xbf15c000,
0xbfffbfd5,0x3fa2bf8e,0xbe49bf8e,0x3fc63fd5,0xbfa2bfed,0xbe493fed,0x3fc63f44,0xbfffbf44,0x3f15bec8,0xbf71bffb,0x3ff53ffb,0x3fe2bec8,
0xbfd5c000,0xbec8c000,0x3f8e0000,0x3ffb0000,0x3ec8bf44,0x3f8e3fed,0x3ffb3fed,0xbfd53f44,0x3ffb3fb5,0xbfd5bfb5,0x3ec83fb5,0x3f8ebfb5,
0x3f8e3fed,0x3ffb3f44,0xbfd5bf44,0xbec83fed,0x3fa20000,0x3fff0000,0x3fc64000,0x3e494000,0x3fe23ffb,0xbff53ec8,0xbf713ec8,0xbf15bffb,
0xbf153f44,0x3fe2bf44,0xbff5bfed,0x3f713fed,0xbfffbfd5,0xbfc63f8e,0x3e49bf8e,0xbfa2bfd5,0x4000,0xbfb54000,0xc0000000,0xbfb50000,
0xc000,0x3fb50000,0x40000000,0xbfb54000,0x4000,0x3fb5c000,0xc0000000,0x3fb50000,0xc000,0xbfb50000,0x40000000,0x3fb5c000,
0xbfff0000,0xbfa20000,0x3e49c000,0x3fc6c000,0x3ff53ec8,0xbfe23ffb,0xbf153ffb,0xbf71bec8,0xbfe2bf44,0x3f153f44,0x3f71bfed,0xbff53fed,
0x3fc63f8e,0x3fffbfd5,0xbfa23fd5,0x3e493f8e,0x3ec8c000,0x3fd5c000,0x3ffb0000,0x3f8e0000,0xbf8e3fed,0xbec8bf44,0xbfd5bf44,0x3ffbbfed,
0x3fd5bfb5,0xbffb3fb5,0x3f8e3fb5,0x3ec8bfb5,0xbffb3f44,0xbf8e3fed,0xbec8bfed,0xbfd53f44,0x3ff50000,0x3f710000,0xbf154000,0xbfe24000,
0xbfa2bf8e,0x3fffbfd5,0x3fc6bfd5,0xbe493f8e,0x3e493fed,0x3fa2bfed,0xbfff3f44,0x3fc6bf44,0x3f71bffb,0xbf15bec8,0x3fe23ec8,0x3ff5bffb,
0xbf444000,0xbfed4000,0xbfed0000,0xbf440000,0x3fedbfb5,0xbf443fb5,0x3f443fb5,0xbfed3fb5,0xbfed0000,0x3f440000,0x3f44c000,0xbfed4000,
0x3f443fb5,0x3fedbfb5,0xbfed3fb5,0xbf443fb5,0xbfe20000,0xbf150000,0x3f71c000,0x3ff5c000,0x3e493fd5,0xbfc63f8e,0xbfff3f8e,0x3fa2bfd5,
0x3fc6bfed,0xbfff3fed,0x3fa23f44,0x3e49bf44,0xbff53ec8,0xbfe23ffb,0x3f15bffb,0xbf713ec8,0x3f8ec000,0x3ffbc000,0x3fd50000,0x3ec80000,
0xbffb3f44,0x3fd5bfed,0x3ec8bfed,0x3f8ebf44,0x3ec83fb5,0x3f8ebfb5,0xbffb3fb5,0x3fd5bfb5,0x3fd5bfed,0x3ec8bf44,0x3f8e3f44,0x3ffbbfed,
0x3fc60000,0x3e490000,0xbfa24000,0xbfff4000,0x3f71bffb,0x3f15bec8,0x3fe2bec8,0xbff53ffb,0xbff53f44,0x3f71bf44,0x3f15bfed,0xbfe23fed,
0xbe493fd5,0x3fa2bf8e,0xbfff3f8e,0xbfc63fd5,0xc0004000,0xbfb54000,0x0,0x3fb50000,0xc0004000,0x3fb50000,0x0,0x3fb5c000,
0xc0004000,0x3fb5c000,0x0,0xbfb50000,0xc0004000,0xbfb50000,0x0,0xbfb54000,0x3e490000,0x3fc60000,0x3fffc000,0x3fa2c000,
0x3f15bec8,0x3f71bffb,0x3ff5bffb,0xbfe23ec8,0x3f71bf44,0xbff53f44,0x3fe2bfed,0xbf153fed,0x3fa2bf8e,0xbe493fd5,0x3fc6bfd5,0x3fffbf8e,
0x3ffbc000,0x3f8ec000,0xbec80000,0xbfd50000,0x3fd5bfed,0xbffb3f44,0xbf8e3f44,0xbec83fed,0x3f8ebfb5,0x3ec83fb5,0xbfd53fb5,0x3ffbbfb5,
0x3ec8bf44,0x3fd5bfed,0xbffb3fed,0xbf8ebf44,0xbf150000,0xbfe20000,0xbff54000,0xbf714000,0xbfc63f8e,0x3e493fd5,0xbfa23fd5,0x3fffbf8e,
0xbfff3fed,0x3fc6bfed,0xbe493f44,0xbfa2bf44,0xbfe23ffb,0xbff53ec8,0x3f71bec8,0xbf153ffb,0xbfed4000,0xbf444000,0x3f440000,0x3fed0000,
0xbf443fb5,0x3fedbfb5,0x3fedbfb5,0xbf44bfb5,0x3f440000,0xbfed0000,0x3fedc000,0xbf444000,0x3fedbfb5,0x3f443fb5,0x3f44bfb5,0x3fedbfb5,
0x3f710000,0x3ff50000,0x3fe2c000,0x3f15c000,0x3fffbfd5,0xbfa2bf8e,0x3e49bf8e,0xbfc63fd5,0x3fa2bfed,0x3e493fed,0xbfc63f44,0x3fffbf44,
0xbf15bec8,0x3f71bffb,0xbff53ffb,0xbfe2bec8,0x3fd5c000,0x3ec8c000,0xbf8e0000,0xbffb0000,0xbec8bf44,0xbf8e3fed,0xbffb3fed,0x3fd53f44,
0xbffb3fb5,0x3fd5bfb5,0xbec83fb5,0xbf8ebfb5,0xbf8e3fed,0xbffb3f44,0x3fd5bf44,0x3ec83fed,0xbfa20000,0xbfff0000,0xbfc64000,0xbe494000,
0xbfe23ffb,0x3ff53ec8,0x3f713ec8,0x3f15bffb,0x3f153f44,0xbfe2bf44,0x3ff5bfed,0xbf713fed,0x3fffbfd5,0x3fc63f8e,0xbe49bf8e,0x3fa2bfd5,
0x4000,0x3fb54000,0x40000000,0x3fb50000,0xc000,0xbfb50000,0xc0000000,0x3fb54000,0x4000,0xbfb5c000,0x40000000,0xbfb50000,
0xc000,0x3fb50000,0xc0000000,0xbfb5c000,0x3fff0000,0x3fa20000,0xbe49c000,0xbfc6c000,0xbff53ec8,0x3fe23ffb,0x3f153ffb,0x3f71bec8,
0x3fe2bf44,0xbf153f44,0xbf71bfed,0x3ff53fed,0xbfc63f8e,0xbfffbfd5,0x3fa23fd5,0xbe493f8e,0xbec8c000,0xbfd5c000,0xbffb0000,0xbf8e0000,
0x3f8e3fed,0x3ec8bf44,0x3fd5bf44,0xbffbbfed,0xbfd5bfb5,0x3ffb3fb5,0xbf8e3fb5,0xbec8bfb5,0x3ffb3f44,0x3f8e3fed,0x3ec8bfed,0x3fd53f44,
0xbff50000,0xbf710000,0x3f154000,0x3fe24000,0x3fa2bf8e,0xbfffbfd5,0xbfc6bfd5,0x3e493f8e,0xbe493fed,0xbfa2bfed,0x3fff3f44,0xbfc6bf44,
0xbf71bffb,0x3f15bec8,0xbfe23ec8,0xbff5bffb,0x3f444000,0x3fed4000,0x3fed0000,0x3f440000,0xbfedbfb5,0x3f443fb5,0xbf443fb5,0x3fed3fb5,
0x3fed0000,0xbf440000,0xbf44c000,0x3fed4000,0xbf443fb5,0xbfedbfb5,0x3fed3fb5,0x3f443fb5,0x3fe20000,0x3f150000,0xbf71c000,0xbff5c000,
0xbe493fd5,0x3fc63f8e,0x3fff3f8e,0xbfa2bfd5,0xbfc6bfed,0x3fff3fed,0xbfa23f44,0xbe49bf44,0x3ff53ec8,0x3fe23ffb,0xbf15bffb,0x3f713ec8,
0xbf8ec000,0xbffbc000,0xbfd50000,0xbec80000,0x3ffb3f44,0xbfd5bfed,0xbec8bfed,0xbf8ebf44,0xbec83fb5,0xbf8ebfb5,0x3ffb3fb5,0xbfd5bfb5,
0xbfd5bfed,0xbec8bf44,0xbf8e3f44,0xbffbbfed,0xbfc60000,0xbe490000,0x3fa24000,0x3fff4000,0xbf71bffb,0xbf15bec8,0xbfe2bec8,0x3ff53ffb,
0x3ff53f44,0xbf71bf44,0xbf15bfed,0x3fe23fed,0x3e493fd5,0xbfa2bf8e,0x3fff3f8e,0x3fc63fd5,0x40004000,0x3fb54000,0x0,0xbfb50000,
0x40004000,0xbfb50000,0x0,0xbfb5c000,0x40004000,0xbfb5c000,0x0,0x3fb50000,0x40004000,0x3fb50000,0x0,0x3fb54000,
0xbfc6bfb5,0xbfffbfb5,0xbfa2bfb5,0x3e49bfb5,0xbfe2bfd5,0x3f15bf8e,0xbf71bf8e,0x3ff53fd5,0xbff5bfed,0x3fe23fed,0xbf15bf44,0xbf713f44,
0xbfffbffb,0xbfa23ec8,0xbe49bec8,0xbfc6bffb,0x3ec80000,0x3fd50000,0x3ffb4000,0x3f8e4000,0x3f8e3f44,0x3ec83fed,0x3fd53fed,0xbffbbf44,
0x3fd53fb5,0xbffbbfb5,0x3f8e3fb5,0x3ec8bfb5,0x3ffb3fed,0x3f8ebf44,0x3ec83f44,0x3fd53fed,0x3f713fb5,0xbf153fb5,0xbfe2bfb5,0xbff5bfb5,
0xbe493ec8,0xbfa2bffb,0xbfffbffb,0x3fc6bec8,0xbfa2bf44,0x3fff3f44,0xbfc6bfed,0x3e493fed,0xbff5bfd5,0xbf713f8e,0xbf15bf8e,0xbfe2bfd5,
0xbfedc000,0xbf44c000,0x3f440000,0x3fed0000,0xbf44bfb5,0x3fed3fb5,0x3fed3fb5,0xbf443fb5,0x3f440000,0xbfed0000,0x3fed4000,0xbf44c000,
0x3fed3fb5,0x3f44bfb5,0x3f443fb5,0x3fed3fb5,0x3ff53fb5,0x3fe23fb5,0x3f153fb5,0xbf713fb5,0x3fc63ffb,0xbfffbec8,0xbfa2bec8,0xbe49bffb,
0xbe493f44,0x3fc6bf44,0xbfffbfed,0x3fa23fed,0xbfe2bf8e,0xbf153fd5,0xbf71bfd5,0xbff5bf8e,0xbf8e0000,0xbffb0000,0xbfd5c000,0xbec8c000,
0xbffbbfed,0x3fd5bf44,0x3ec8bf44,0x3f8e3fed,0xbec8bfb5,0xbf8e3fb5,0x3ffb3fb5,0xbfd5bfb5,0x3fd53f44,0x3ec8bfed,0x3f8e3fed,0x3ffb3f44,
0xbe49bfb5,0x3fa2bfb5,0x3fff3fb5,0x3fc63fb5,0x3ff53f8e,0xbf713fd5,0x3f153fd5,0xbfe2bf8e,0x3f713fed,0x3f15bfed,0xbfe2bf44,0x3ff53f44,
0xbfc6bec8,0xbe493ffb,0xbfa2bffb,0xbfffbec8,0x4000,0xbfb54000,0xc0000000,0xbfb50000,0xc000,0x3fb50000,0x40000000,0xbfb54000,
0x4000,0x3fb5c000,0xc0000000,0x3fb50000,0xc000,0xbfb50000,0x40000000,0x3fb5c000,0xbfa2bfb5,0x3e49bfb5,0x3fc6bfb5,0x3fffbfb5,
0x3f713fd5,0xbff53f8e,0xbfe23f8e,0x3f15bfd5,0xbf15bfed,0xbf713fed,0x3ff5bf44,0xbfe23f44,0x3e493ffb,0x3fc6bec8,0xbfff3ec8,0xbfa23ffb,
0x3ffb0000,0x3f8e0000,0xbec84000,0xbfd54000,0xbfd5bf44,0x3ffbbfed,0x3f8ebfed,0x3ec83f44,0x3f8e3fb5,0x3ec8bfb5,0xbfd53fb5,0x3ffbbfb5,
0xbec8bfed,0xbfd53f44,0x3ffbbf44,0x3f8ebfed,0xbfe23fb5,0xbff53fb5,0xbf71bfb5,0x3f15bfb5,0x3fffbec8,0xbfc63ffb,0xbe493ffb,0xbfa23ec8,
0xbfc6bf44,0x3e493f44,0x3fa2bfed,0xbfff3fed,0x3f153fd5,0x3fe2bf8e,0xbff53f8e,0xbf713fd5,0x3f44c000,0x3fedc000,0x3fed0000,0x3f440000,
0xbfed3fb5,0x3f44bfb5,0xbf44bfb5,0x3fedbfb5,0x3fed0000,0xbf440000,0xbf444000,0x3fedc000,0xbf44bfb5,0xbfed3fb5,0x3fedbfb5,0x3f44bfb5,
0x3f153fb5,0xbf713fb5,0xbff53fb5,0xbfe23fb5,0x3fa2bffb,0x3e493ec8,0x3fc63ec8,0xbfff3ffb,0xbfff3f44,0x3fa2bf44,0x3e49bfed,0xbfc63fed,
0x3f713f8e,0x3ff5bfd5,0xbfe23fd5,0xbf153f8e,0xbfd50000,0xbec80000,0x3f8ec000,0x3ffbc000,0xbec83fed,0xbf8e3f44,0xbffb3f44,0x3fd5bfed,
0x3ffbbfb5,0xbfd53fb5,0x3ec83fb5,0x3f8ebfb5,0xbf8ebf44,0xbffb3fed,0x3fd5bfed,0x3ec8bf44,0x3fffbfb5,0x3fc6bfb5,0x3e493fb5,0xbfa23fb5,
0xbf15bf8e,0x3fe2bfd5,0x3ff5bfd5,0xbf713f8e,0xbfe23fed,0x3ff5bfed,0xbf71bf44,0xbf153f44,0x3fa23ec8,0x3fffbffb,0xbfc63ffb,0xbe493ec8,
0xc0004000,0xbfb54000,0x0,0x3fb50000,0xc0004000,0x3fb50000,0x0,0x3fb5c000,0xc0004000,0x3fb5c000,0x0,0xbfb50000,
0xc0004000,0xbfb50000,0x0,0xbfb54000,0x3fc6bfb5,0x3fffbfb5,0x3fa2bfb5,0xbe49bfb5,0x3fe2bfd5,0xbf15bf8e,0x3f71bf8e,0xbff53fd5,
0x3ff5bfed,0xbfe23fed,0x3f15bf44,0x3f713f44,0x3fffbffb,0x3fa23ec8,0x3e49bec8,0x3fc6bffb,0xbec80000,0xbfd50000,0xbffb4000,0xbf8e4000,
0xbf8e3f44,0xbec83fed,0xbfd53fed,0x3ffbbf44,0xbfd53fb5,0x3ffbbfb5,0xbf8e3fb5,0xbec8bfb5,0xbffb3fed,0xbf8ebf44,0xbec83f44,0xbfd53fed,
0xbf713fb5,0x3f153fb5,0x3fe2bfb5,0x3ff5bfb5,0x3e493ec8,0x3fa2bffb,0x3fffbffb,0xbfc6bec8,0x3fa2bf44,0xbfff3f44,0x3fc6bfed,0xbe493fed,
0x3ff5bfd5,0x3f713f8e,0x3f15bf8e,0x3fe2bfd5,0x3fedc000,0x3f44c000,0xbf440000,0xbfed0000,0x3f44bfb5,0xbfed3fb5,0xbfed3fb5,0x3f443fb5,
0xbf440000,0x3fed0000,0xbfed4000,0x3f44c000,0xbfed3fb5,0xbf44bfb5,0xbf443fb5,0xbfed3fb5,0xbff53fb5,0xbfe23fb5,0xbf153fb5,0x3f713fb5,
0xbfc63ffb,0x3fffbec8,0x3fa2bec8,0x3e49bffb,0x3e493f44,0xbfc6bf44,0x3fffbfed,0xbfa23fed,0x3fe2bf8e,0x3f153fd5,0x3f71bfd5,0x3ff5bf8e,
0x3f8e0000,0x3ffb0000,0x3fd5c000,0x3ec8c000,0x3ffbbfed,0xbfd5bf44,0xbec8bf44,0xbf8e3fed,0x3ec8bfb5,0x3f8e3fb5,0xbffb3fb5,0x3fd5bfb5,
0xbfd53f44,0xbec8bfed,0xbf8e3fed,0xbffb3f44,0x3e49bfb5,0xbfa2bfb5,0xbfff3fb5,0xbfc63fb5,0xbff53f8e,0x3f713fd5,0xbf153fd5,0x3fe2bf8e,
0xbf713fed,0xbf15bfed,0x3fe2bf44,0xbff53f44,0x3fc6bec8,0x3e493ffb,0x3fa2bffb,0x3fffbec8,0x4000,0x3fb54000,0x40000000,0x3fb50000,
0xc000,0xbfb50000,0xc0000000,0x3fb54000,0x4000,0xbfb5c000,0x40000000,0xbfb50000,0xc000,0x3fb50000,0xc0000000,0xbfb5c000,
0x3fa2bfb5,0xbe49bfb5,0xbfc6bfb5,0xbfffbfb5,0xbf713fd5,0x3ff53f8e,0x3fe23f8e,0xbf15bfd5,0x3f15bfed,0x3f713fed,0xbff5bf44,0x3fe23f44,
0xbe493ffb,0xbfc6bec8,0x3fff3ec8,0x3fa23ffb,0xbffb0000,0xbf8e0000,0x3ec84000,0x3fd54000,0x3fd5bf44,0xbffbbfed,0xbf8ebfed,0xbec83f44,
0xbf8e3fb5,0xbec8bfb5,0x3fd53fb5,0xbffbbfb5,0x3ec8bfed,0x3fd53f44,0xbffbbf44,0xbf8ebfed,0x3fe23fb5,0x3ff53fb5,0x3f71bfb5,0xbf15bfb5,
0xbfffbec8,0x3fc63ffb,0x3e493ffb,0x3fa23ec8,0x3fc6bf44,0xbe493f44,0xbfa2bfed,0x3fff3fed,0xbf153fd5,0xbfe2bf8e,0x3ff53f8e,0x3f713fd5,
0xbf44c000,0xbfedc000,0xbfed0000,0xbf440000,0x3fed3fb5,0xbf44bfb5,0x3f44bfb5,0xbfedbfb5,0xbfed0000,0x3f440000,0x3f444000,0xbfedc000,
0x3f44bfb5,0x3fed3fb5,0xbfedbfb5,0xbf44bfb5,0xbf153fb5,0x3f713fb5,0x3ff53fb5,0x3fe23fb5,0xbfa2bffb,0xbe493ec8,0xbfc63ec8,0x3fff3ffb,
0x3fff3f44,0xbfa2bf44,0xbe49bfed,0x3fc63fed,0xbf713f8e,0xbff5bfd5,0x3fe23fd5,0x3f153f8e,0x3fd50000,0x3ec80000,0xbf8ec000,0xbffbc000,
0x3ec83fed,0x3f8e3f44,0x3ffb3f44,0xbfd5bfed,0xbffbbfb5,0x3fd53fb5,0xbec83fb5,0xbf8ebfb5,0x3f8ebf44,0x3ffb3fed,0xbfd5bfed,0xbec8bf44,
0xbfffbfb5,0xbfc6bfb5,0xbe493fb5,0x3fa23fb5,0x3f15bf8e,0xbfe2bfd5,0xbff5bfd5,0x3f713f8e,0x3fe23fed,0xbff5bfed,0x3f71bf44,0x3f153f44,
0xbfa23ec8,0xbfffbffb,0x3fc63ffb,0x3e493ec8,0x80003f80,0x3f800000,0x80003f80,0x3f800000,0x80003f80,0x3f800000,0x80003f80,0x3f800000,
0x80003f80,0x3f800000,0x80003f80,0x3f800000,0x80003f80,0x3f800000,0x80003f80,0x3f800000,0x80003f80,0x3f800000,0x8000bf80,0xbf800000,
0x3f353f35,0x3f35bf35,0xbf35bf35,0xbf353f35,0x3f800000,0xbf80,0xbf800000,0x3f80,0x3f35bf35,0xbf35bf35,0xbf353f35,0x3f353f35,
0x80003f80,0x3f800000,0x80003f80,0x3f800000,0x3f800000,0xbf80,0x3f800000,0xbf80,0x8000bf80,0xbf800000,0x8000bf80,0xbf800000,
0xbf800000,0x3f80,0xbf800000,0x3f80,0x80003f80,0x3f800000,0x8000bf80,0xbf800000,0x3f35bf35,0xbf35bf35,0xbf353f35,0x3f353f35,
0xbf800000,0x3f80,0x3f800000,0xbf80,0x3f353f35,0x3f35bf35,0xbf35bf35,0xbf353f35,0x80003f80,0x3f800000,0x80003f80,0x3f800000,
0x8000bf80,0xbf800000,0x8000bf80,0xbf800000,0x80003f80,0x3f800000,0x80003f80,0x3f800000,0x8000bf80,0xbf800000,0x8000bf80,0xbf800000,
0x80003f80,0x3f800000,0x8000bf80,0xbf800000,0xbf35bf35,0xbf353f35,0x3f353f35,0x3f35bf35,0x3f800000,0xbf80,0xbf800000,0x3f80,
0xbf353f35,0x3f353f35,0x3f35bf35,0xbf35bf35,0x80003f80,0x3f800000,0x80003f80,0x3f800000,0xbf800000,0x3f80,0xbf800000,0x3f80,
0x8000bf80,0xbf800000,0x8000bf80,0xbf800000,0x3f800000,0xbf80,0x3f800000,0xbf80,0x80003f80,0x3f800000,0x8000bf80,0xbf800000,
0xbf353f35,0x3f353f35,0x3f35bf35,0xbf35bf35,0xbf800000,0x3f80,0x3f800000,0xbf80,0xbf35bf35,0xbf353f35,0x3f353f35,0x3f35bf35,
0x3f803f80,0x80008000,0x80008000,0xbf80bf80,0x3f803f80,0x80008000,0x80008000,0xbf80bf80,0x3f803f80,0x80008000,0x80008000,0xbf80bf80,
0x3f803f80,0x80008000,0x80008000,0xbf80bf80,0x3f353f80,0x3f358000,0x3f358000,0xbf35bf80,0xbf350000,0x3f353f80,0x3f353f80,0x3f358000,
0xbf35bf80,0xbf358000,0xbf358000,0x3f353f80,0x3f350000,0xbf35bf80,0xbf35bf80,0xbf358000,0x3f80,0x3f808000,0x3f808000,0x8000bf80,
0xbf80,0xbf808000,0xbf808000,0x80003f80,0x3f80,0x3f808000,0x3f808000,0x8000bf80,0xbf80,0xbf808000,0xbf808000,0x80003f80,
0xbf353f80,0x3f358000,0x3f358000,0x3f35bf80,0x3f350000,0x3f35bf80,0x3f35bf80,0xbf358000,0x3f35bf80,0xbf358000,0xbf358000,0xbf353f80,
0xbf350000,0xbf353f80,0xbf353f80,0x3f358000,0xbf803f80,0x80008000,0x80008000,0x3f80bf80,0xbf803f80,0x80008000,0x80008000,0x3f80bf80,
0xbf803f80,0x80008000,0x80008000,0x3f80bf80,0xbf803f80,0x80008000,0x80008000,0x3f80bf80,0xbf353f80,0xbf358000,0xbf358000,0x3f35bf80,
0x3f350000,0xbf353f80,0xbf353f80,0xbf358000,0x3f35bf80,0x3f358000,0x3f358000,0xbf353f80,0xbf350000,0x3f35bf80,0x3f35bf80,0x3f358000,
0x3f80,0xbf808000,0xbf808000,0x8000bf80,0xbf80,0x3f808000,0x3f808000,0x80003f80,0x3f80,0xbf808000,0xbf808000,0x8000bf80,
0xbf80,0x3f808000,0x3f808000,0x80003f80,0x3f353f80,0xbf358000,0xbf358000,0xbf35bf80,0xbf350000,0xbf35bf80,0xbf35bf80,0x3f358000,
0xbf35bf80,0x3f358000,0x3f358000,0x3f353f80,0x3f350000,0x3f353f80,0x3f353f80,0xbf358000,0x3f800000,0x0,0x3f800000,0x0,
0x3f800000,0x0,0x3f800000,0x0,0x3f800000,0x0,0x3f800000,0x0,0x3f800000,0x0,0x3f800000,0x0,
0x3f800000,0x0,0x3f7fb10f,0xbd48fb30,0x3f7ec46d,0xbdc8bd36,0x3f7d3aac,0xbe164083,0x3f7b14be,0xbe47c5c2,0x3f7853f8,0xbe78cfcc,
0x3f74fa0b,0xbe94a031,0x3f710908,0xbeac7cd4,0x3f800000,0x0,0x3f7ec46d,0xbdc8bd36,0x3f7b14be,0xbe47c5c2,0x3f74fa0b,0xbe94a031,
0x3f6c835e,0xbec3ef15,0x3f61c598,0xbef15aea,0x3f54db31,0xbf0e39da,0x3f45e403,0xbf226799,0x3f800000,0x0,0x3f7d3aac,0xbe164083,
0x3f74fa0b,0xbe94a031,0x3f676bd8,0xbedae880,0x3f54db31,0xbf0e39da,0x3f3daef9,0xbf2beb4a,0x3f226799,0xbf45e403,0x3f039c3d,0xbf5b941a,
0x3f800000,0x0,0x3f7b14be,0xbe47c5c2,0x3f6c835e,0xbec3ef15,0x3f54db31,0xbf0e39da,0x3f3504f3,0xbf3504f3,0x3f0e39da,0xbf54db31,
0x3ec3ef15,0xbf6c835e,0x3e47c5c2,0xbf7b14be,0x3f800000,0x0,0x3f7853f8,0xbe78cfcc,0x3f61c598,0xbef15aea,0x3f3daef9,0xbf2beb4a,
0x3f0e39da,0xbf54db31,0x3eac7cd4,0xbf710908,0x3dc8bd36,0xbf7ec46d,0xbe164083,0xbf7d3aac,0x3f800000,0x0,0x3f74fa0b,0xbe94a031,
0x3f54db31,0xbf0e39da,0x3f226799,0xbf45e403,0x3ec3ef15,0xbf6c835e,0x3dc8bd36,0xbf7ec46d,0xbe47c5c2,0xbf7b14be,0xbef15aea,0xbf61c598,
0x3f800000,0x0,0x3f710908,0xbeac7cd4,0x3f45e403,0xbf226799,0x3f039c3d,0xbf5b941a,0x3e47c5c2,0xbf7b14be,0xbe164083,0xbf7d3aac,
0xbef15aea,0xbf61c598,0xbf3daef9,0xbf2beb4a,0x3f800000,0x0,0x3f800000,0x0,0x3f800000,0x0,0x3f800000,0x0,
0x3f800000,0x0,0x3f800000,0x0,0x3f800000,0x0,0x3f800000,0x0,0x3f6c835e,0xbec3ef15,0x3f676bd8,0xbedae880,
0x3f61c598,0xbef15aea,0x3f5b941a,0xbf039c3d,0x3f54db31,0xbf0e39da,0x3f4d9f02,0xbf187fc0,0x3f45e403,0xbf226799,0x3f3daef9,0xbf2beb4a,
0x3f3504f3,0xbf3504f3,0x3f226799,0xbf45e403,0x3f0e39da,0xbf54db31,0x3ef15aea,0xbf61c598,0x3ec3ef15,0xbf6c835e,0x3e94a031,0xbf74fa0b,
0x3e47c5c2,0xbf7b14be,0x3dc8bd36,0xbf7ec46d,0x3ec3ef15,0xbf6c835e,0x3e78cfcc,0xbf7853f8,0x3dc8bd36,0xbf7ec46d,0xbd48fb30,0xbf7fb10f,
0xbe47c5c2,0xbf7b14be,0xbeac7cd4,0xbf710908,0xbef15aea,0xbf61c598,0xbf187fc0,0xbf4d9f02,0x0,0xbf800000,0xbe47c5c2,0xbf7b14be,
0xbec3ef15,0xbf6c835e,0xbf0e39da,0xbf54db31,0xbf3504f3,0xbf3504f3,0xbf54db31,0xbf0e39da,0xbf6c835e,0xbec3ef15,0xbf7b14be,0xbe47c5c2,
0xbec3ef15,0xbf6c835e,0xbf187fc0,0xbf4d9f02,0xbf45e403,0xbf226799,0xbf676bd8,0xbedae880,0xbf7b14be,0xbe47c5c2,0xbf7fb10f,0x3d48fb30,
0xbf74fa0b,0x3e94a031,0xbf5b941a,0x3f039c3d,0xbf3504f3,0xbf3504f3,0xbf61c598,0xbef15aea,0xbf7b14be,0xbe47c5c2,0xbf7ec46d,0x3dc8bd36,
0xbf6c835e,0x3ec3ef15,0xbf45e403,0x3f226799,0xbf0e39da,0x3f54db31,0xbe94a031,0x3f74fa0b,0xbf6c835e,0xbec3ef15,0xbf7fb10f,0xbd48fb30,
0xbf74fa0b,0x3e94a031,0xbf4d9f02,0x3f187fc0,0xbf0e39da,0x3f54db31,0xbe78cfcc,0x3f7853f8,0x3dc8bd36,0x3f7ec46d,0x3edae880,0x3f676bd8,
0x80003f80,0x3f800000,0x3f800000,0xbf80,0x3ec43f6d,0x3f6dbec4,0x3f6dbec4,0xbec4bf6d,0x3f353f35,0x3f35bf35,0x3f35bf35,0xbf35bf35,
0x3f6d3ec4,0x3ec4bf6d,0x3ec4bf6d,0xbf6dbec4,0x80003f80,0x3f800000,0xbf800000,0x3f80,0x3f6d3ec4,0x3ec4bf6d,0xbec43f6d,0x3f6d3ec4,
0x3f35bf35,0xbf35bf35,0x3f353f35,0x3f35bf35,0xbec4bf6d,0xbf6d3ec4,0x3f6dbec4,0xbec4bf6d,0x80003f80,0x3f800000,0x3f800000,0xbf80,
0x3f6dbec4,0xbec4bf6d,0xbec4bf6d,0xbf6d3ec4,0xbf35bf35,0xbf353f35,0xbf353f35,0x3f353f35,0xbec43f6d,0x3f6d3ec4,0x3f6d3ec4,0x3ec4bf6d,
0x80003f80,0x3f800000,0xbf800000,0x3f80,0x3ec4bf6d,0xbf6dbec4,0x3f6d3ec4,0x3ec4bf6d,0xbf353f35,0x3f353f35,0xbf35bf35,0xbf353f35,
0x3f6dbec4,0xbec4bf6d,0x3ec43f6d,0x3f6dbec4,0x80003f80,0x3f800000,0x3f800000,0xbf80,0xbec4bf6d,0xbf6d3ec4,0xbf6d3ec4,0x3ec43f6d,
0x3f353f35,0x3f35bf35,0x3f35bf35,0xbf35bf35,0xbf6dbec4,0xbec43f6d,0xbec43f6d,0x3f6d3ec4,0x80003f80,0x3f800000,0xbf800000,0x3f80,
0xbf6dbec4,0xbec43f6d,0x3ec4bf6d,0xbf6dbec4,0x3f35bf35,0xbf35bf35,0x3f353f35,0x3f35bf35,0x3ec43f6d,0x3f6dbec4,0xbf6d3ec4,0x3ec43f6d,
0x80003f80,0x3f800000,0x3f800000,0xbf80,0xbf6d3ec4,0x3ec43f6d,0x3ec43f6d,0x3f6dbec4,0xbf35bf35,0xbf353f35,0xbf353f35,0x3f353f35,
0x3ec4bf6d,0xbf6dbec4,0xbf6dbec4,0xbec43f6d,0x80003f80,0x3f800000,0xbf800000,0x3f80,0xbec43f6d,0x3f6d3ec4,0xbf6dbec4,0xbec43f6d,
0xbf353f35,0x3f353f35,0xbf35bf35,0xbf353f35,0xbf6d3ec4,0x3ec43f6d,0xbec4bf6d,0xbf6d3ec4,0x3f803f80,0x80008000,0x80008000,0xbf80bf80,
0x3f803f80,0x80008000,0x80008000,0xbf80bf80,0x3f803f80,0x80008000,0x80008000,0xbf80bf80,0x3f803f80,0x80008000,0x80008000,0xbf80bf80,
0x3ec43f6d,0x3f6d3ec4,0x3f6d3ec4,0xbec4bf6d,0xbf6dbec4,0x3ec43f6d,0x3ec43f6d,0x3f6d3ec4,0xbec4bf6d,0xbf6dbec4,0xbf6dbec4,0x3ec43f6d,
0x3f6d3ec4,0xbec4bf6d,0xbec4bf6d,0xbf6dbec4,0xbf353f35,0x3f353f35,0x3f353f35,0x3f35bf35,0x3f35bf35,0xbf35bf35,0xbf35bf35,0xbf353f35,
0xbf353f35,0x3f353f35,0x3f353f35,0x3f35bf35,0x3f35bf35,0xbf35bf35,0xbf35bf35,0xbf353f35,0xbf6d3ec4,0xbec43f6d,0xbec43f6d,0x3f6dbec4,
0xbec43f6d,0x3f6dbec4,0x3f6dbec4,0x3ec4bf6d,0x3f6dbec4,0x3ec4bf6d,0x3ec4bf6d,0xbf6d3ec4,0x3ec4bf6d,0xbf6d3ec4,0xbf6d3ec4,0xbec43f6d,
0x0,0xbf803f80,0xbf803f80,0x80008000,0x0,0xbf803f80,0xbf803f80,0x80008000,0x0,0xbf803f80,0xbf803f80,0x80008000,
0x0,0xbf803f80,0xbf803f80,0x80008000,0x3f6dbec4,0xbec43f6d,0xbec43f6d,0xbf6d3ec4,0x3ec4bf6d,0x3f6dbec4,0x3f6dbec4,0xbec43f6d,
0xbf6d3ec4,0x3ec4bf6d,0x3ec4bf6d,0x3f6dbec4,0xbec43f6d,0xbf6d3ec4,0xbf6d3ec4,0x3ec4bf6d,0x3f35bf35,0x3f353f35,0x3f353f35,0xbf353f35,
0xbf353f35,0xbf35bf35,0xbf35bf35,0x3f35bf35,0x3f35bf35,0x3f353f35,0x3f353f35,0xbf353f35,0xbf353f35,0xbf35bf35,0xbf35bf35,0x3f35bf35,
0xbec4bf6d,0x3f6d3ec4,0x3f6d3ec4,0x3ec43f6d,0x3f6d3ec4,0x3ec43f6d,0x3ec43f6d,0xbf6dbec4,0x3ec43f6d,0xbf6dbec4,0xbf6dbec4,0xbec4bf6d,
0xbf6dbec4,0xbec4bf6d,0xbec4bf6d,0x3f6d3ec4,0x3f800000,0x0,0x3f7fec43,0xbcc90ab0,0x3f7fb10f,0xbd48fb30,0x3f7f4e6d,0xbd96a905,
0x3f7ec46d,0xbdc8bd36,0x3f7e1324,0xbdfab273,0x3f7d3aac,0xbe164083,0x3f7c3b28,0xbe2f10a2,0x3f800000,0x0,0x3f7f4e6d,0xbd96a905,
0x3f7d3aac,0xbe164083,0x3f79c79d,0xbe605c13,0x3f74fa0b,0xbe94a031,0x3f6ed89e,0xbeb8442a,0x3f676bd8,0xbedae880,0x3f5ebe05,0xbefc5d27,
0x3f800000,0x0,0x3f7e1324,0xbdfab273,0x3f7853f8,0xbe78cfcc,0x3f6ed89e,0xbeb8442a,0x3f61c598,0xbef15aea,0x3f514d3d,0xbf13682a,
0x3f3daef9,0xbf2beb4a,0x3f273656,0xbf41d870,0x3f800000,0x0,0x3f7c3b28,0xbe2f10a2,0x3f710908,0xbeac7cd4,0x3f5ebe05,0xbefc5d27,
0x3f45e403,0xbf226799,0x3f273656,0xbf41d870,0x3f039c3d,0xbf5b941a,0x3eb8442a,0xbf6ed89e,0x3f800000,0x0,0x3f79c79d,0xbe605c13,
0x3f676bd8,0xbedae880,0x3f49d112,0xbf1d7fd1,0x3f226799,0xbf45e403,0x3ee63375,0xbf64aa59,0x3e78cfcc,0xbf7853f8,0x3cc90ab0,0xbf7fec43,
0x3f800000,0x0,0x3f76ba07,0xbe888e93,0x3f5b941a,0xbf039c3d,0x3f3085bb,0xbf396842,0x3ef15aea,0xbf61c598,0x3e605c13,0xbf79c79d,
0xbd48fb30,0xbf7fb10f,0xbea09ae5,0xbf731447,0x3f800000,0x0,0x3f731447,0xbea09ae5,0x3f4d9f02,0xbf187fc0,0x3f13682a,0xbf514d3d,
0x3e94a031,0xbf74fa0b,0xbcc90ab0,0xbf7fec43,0xbeac7cd4,0xbf710908,0xbf1d7fd1,0xbf49d112,0x3f800000,0x0,0x3f6ed89e,0xbeb8442a,
0x3f3daef9,0xbf2beb4a,0x3ee63375,0xbf64aa59,0x3dc8bd36,0xbf7ec46d,0xbe888e93,0xbf76ba07,0xbf187fc0,0xbf4d9f02,0xbf584853,0xbf08f59b,
0x3f7b14be,0xbe47c5c2,0x3f79c79d,0xbe605c13,0x3f7853f8,0xbe78cfcc,0x3f76ba07,0xbe888e93,0x3f74fa0b,0xbe94a031,0x3f731447,0xbea09ae5,
0x3f710908,0xbeac7cd4,0x3f6ed89e,0xbeb8442a,0x3f54db31,0xbf0e39da,0x3f49d112,0xbf1d7fd1,0x3f3daef9,0xbf2beb4a,0x3f3085bb,0xbf396842,
0x3f226799,0xbf45e403,0x3f13682a,0xbf514d3d,0x3f039c3d,0xbf5b941a,0x3ee63375,0xbf64aa59,0x3f0e39da,0xbf54db31,0x3ee63375,0xbf64aa59,
0x3eac7cd4,0xbf710908,0x3e605c13,0xbf79c79d,0x3dc8bd36,0xbf7ec46d,0xbcc90ab0,0xbf7fec43,0xbe164083,0xbf7d3aac,0xbe888e93,0xbf76ba07,
0x3e47c5c2,0xbf7b14be,0x3cc90ab0,0xbf7fec43,0xbe164083,0xbf7d3aac,0xbea09ae5,0xbf731447,0xbef15aea,0xbf61c598,0xbf1d7fd1,0xbf49d112,
0xbf3daef9,0xbf2beb4a,0xbf584853,0xbf08f59b,0xbe47c5c2,0xbf7b14be,0xbecf7bca,0xbf6a09a7,0xbf187fc0,0xbf4d9f02,0xbf41d870,0xbf273656,
0xbf61c598,0xbef15aea,0xbf76ba07,0xbe888e93,0xbf7fb10f,0xbd48fb30,0xbf7c3b28,0x3e2f10a2,0xbf0e39da,0xbf54db31,0xbf41d870,0xbf273656,
0xbf676bd8,0xbedae880,0xbf7c3b28,0xbe2f10a2,0xbf7ec46d,0x3dc8bd36,0xbf6ed89e,0x3eb8442a,0xbf4d9f02,0x3f187fc0,0xbf1d7fd1,0x3f49d112,
0xbf54db31,0xbf0e39da,0xbf76ba07,0xbe888e93,0xbf7fb10f,0x3d48fb30,0xbf6ed89e,0x3eb8442a,0xbf45e403,0x3f226799,0xbf08f59b,0x3f584853,
0xbe78cfcc,0x3f7853f8,0x3d96a905,0x3f7f4e6d,0xbf7b14be,0xbe47c5c2,0xbf7c3b28,0x3e2f10a2,0xbf5b941a,0x3f039c3d,0xbf1d7fd1,0x3f49d112,
0xbe94a031,0x3f74fa0b,0x3d96a905,0x3f7f4e6d,0x3edae880,0x3f676bd8,0x3f396842,0x3f3085bb,0x80003f80,0x80003f80,0x80003f80,0x80003f80,
0x80003f80,0x80003f80,0x80003f80,0x80003f80,0x80003f80,0x80003f80,0x80003f80,0x80003f80,0x80003f80,0x80003f80,0x80003f80,0x80003f80,
0x3f800000,0x3f800000,0x3f800000,0x3f800000,0x3f800000,0x3f800000,0x3f800000,0x3f800000,0x3f800000,0x3f800000,0x3f800000,0x3f800000,
0x3f800000,0x3f800000,0x3f800000,0x3f800000,0x80003f80,0x3f353f35,0x80003f80,0x3f353f35,0x3f800000,0x3f35bf35,0x3f800000,0x3f35bf35,
0x8000bf80,0xbf35bf35,0x8000bf80,0xbf35bf35,0xbf800000,0xbf353f35,0xbf800000,0xbf353f35,0x3f800000,0x3f35bf35,0x3f800000,0x3f35bf35,
0xbf80,0xbf35bf35,0xbf80,0xbf35bf35,0xbf800000,0xbf353f35,0xbf800000,0xbf353f35,0x3f80,0x3f353f35,0x3f80,0x3f353f35,
0x80003f80,0x3f800000,0x80003f80,0x3f800000,0x8000bf80,0xbf800000,0x8000bf80,0xbf800000,0x80003f80,0x3f800000,0x80003f80,0x3f800000,
0x8000bf80,0xbf800000,0x8000bf80,0xbf800000,0x3f800000,0xbf80,0x3f800000,0xbf80,0xbf800000,0x3f80,0xbf800000,0x3f80,
0x3f800000,0xbf80,0x3f800000,0xbf80,0xbf800000,0x3f80,0xbf800000,0x3f80,0x80003f80,0x3f35bf35,0x80003f80,0x3f35bf35,
0xbf800000,0x3f353f35,0xbf800000,0x3f353f35,0x8000bf80,0xbf353f35,0x8000bf80,0xbf353f35,0x3f800000,0xbf35bf35,0x3f800000,0xbf35bf35,
0x3f800000,0xbf35bf35,0x3f800000,0xbf35bf35,0x3f80,0x3f35bf35,0x3f80,0x3f35bf35,0xbf800000,0x3f353f35,0xbf800000,0x3f353f35,
0xbf80,0xbf353f35,0xbf80,0xbf353f35,0x80003f80,0x3ec43f6d,0x8000bf80,0xbec4bf6d,0x3f353f35,0x3f6d3ec4,0xbf35bf35,0xbf6dbec4,
0x3f800000,0x3f6dbec4,0xbf800000,0xbf6d3ec4,0x3f35bf35,0x3ec4bf6d,0xbf353f35,0xbec43f6d,0x3f800000,0x3f6dbec4,0xbf800000,0xbf6d3ec4,
0x3f35bf35,0x3ec4bf6d,0xbf353f35,0xbec43f6d,0xbf80,0xbec4bf6d,0x3f80,0x3ec43f6d,0xbf35bf35,0xbf6dbec4,0x3f353f35,0x3f6d3ec4,
0x80003f80,0x3f6d3ec4,0x8000bf80,0xbf6dbec4,0x3f35bf35,0xbec4bf6d,0xbf353f35,0x3ec43f6d,0xbf800000,0xbec43f6d,0x3f800000,0x3ec4bf6d,
0x3f353f35,0x3f6dbec4,0xbf35bf35,0xbf6d3ec4,0x3f800000,0x3ec4bf6d,0xbf800000,0xbec43f6d,0xbf35bf35,0xbf6d3ec4,0x3f353f35,0x3f6dbec4,
0x3f80,0x3f6d3ec4,0xbf80,0xbf6dbec4,0x3f35bf35,0xbec4bf6d,0xbf353f35,0x3ec43f6d,0x80003f80,0x3f6dbec4,0x8000bf80,0xbf6d3ec4,
0xbf35bf35,0xbec43f6d,0x3f353f35,0x3ec4bf6d,0x3f800000,0xbec4bf6d,0xbf800000,0x3ec43f6d,0xbf353f35,0x3f6d3ec4,0x3f35bf35,0xbf6dbec4,
0x3f800000,0xbec4bf6d,0xbf800000,0x3ec43f6d,0xbf353f35,0x3f6d3ec4,0x3f35bf35,0xbf6dbec4,0xbf80,0xbf6d3ec4,0x3f80,0x3f6dbec4,
0x3f353f35,0x3ec4bf6d,0xbf35bf35,0xbec43f6d,0x80003f80,0x3ec4bf6d,0x8000bf80,0xbec43f6d,0xbf353f35,0x3f6dbec4,0x3f35bf35,0xbf6d3ec4,
0xbf800000,0x3f6d3ec4,0x3f800000,0xbf6dbec4,0xbf35bf35,0x3ec43f6d,0x3f353f35,0xbec4bf6d,0x3f800000,0xbf6dbec4,0xbf800000,0x3f6d3ec4,
0x3f353f35,0xbec4bf6d,0xbf35bf35,0x3ec43f6d,0x3f80,0x3ec4bf6d,0xbf80,0xbec43f6d,0xbf353f35,0x3f6dbec4,0x3f35bf35,0xbf6d3ec4,
0x80003f80,0x8000bf80,0x80003f80,0x8000bf80,0x80003f80,0x8000bf80,0x80003f80,0x8000bf80,0x80003f80,0x8000bf80,0x80003f80,0x8000bf80,
0x80003f80,0x8000bf80,0x80003f80,0x8000bf80,0x3f800000,0xbf800000,0x3f800000,0xbf800000,0x3f800000,0xbf800000,0x3f800000,0xbf800000,
0x3f800000,0xbf800000,0x3f800000,0xbf800000,0x3f800000,0xbf800000,0x3f800000,0xbf800000,0x80003f80,0xbf35bf35,0x80003f80,0xbf35bf35,
0x3f800000,0xbf353f35,0x3f800000,0xbf353f35,0x8000bf80,0x3f353f35,0x8000bf80,0x3f353f35,0xbf800000,0x3f35bf35,0xbf800000,0x3f35bf35,
0x3f800000,0xbf353f35,0x3f800000,0xbf353f35,0xbf80,0x3f353f35,0xbf80,0x3f353f35,0xbf800000,0x3f35bf35,0xbf800000,0x3f35bf35,
0x3f80,0xbf35bf35,0x3f80,0xbf35bf35,0x80003f80,0xbf800000,0x80003f80,0xbf800000,0x8000bf80,0x3f800000,0x8000bf80,0x3f800000,
0x80003f80,0xbf800000,0x80003f80,0xbf800000,0x8000bf80,0x3f800000,0x8000bf80,0x3f800000,0x3f800000,0x3f80,0x3f800000,0x3f80,
0xbf800000,0xbf80,0xbf800000,0xbf80,0x3f800000,0x3f80,0x3f800000,0x3f80,0xbf800000,0xbf80,0xbf800000,0xbf80,
0x80003f80,0xbf353f35,0x80003f80,0xbf353f35,0xbf800000,0xbf35bf35,0xbf800000,0xbf35bf35,0x8000bf80,0x3f35bf35,0x8000bf80,0x3f35bf35,
0x3f800000,0x3f353f35,0x3f800000,0x3f353f35,0x3f800000,0x3f353f35,0x3f800000,0x3f353f35,0x3f80,0xbf353f35,0x3f80,0xbf353f35,
0xbf800000,0xbf35bf35,0xbf800000,0xbf35bf35,0xbf80,0x3f35bf35,0xbf80,0x3f35bf35,0x80003f80,0xbec4bf6d,0x8000bf80,0x3ec43f6d,
0x3f353f35,0xbf6dbec4,0xbf35bf35,0x3f6d3ec4,0x3f800000,0xbf6d3ec4,0xbf800000,0x3f6dbec4,0x3f35bf35,0xbec43f6d,0xbf353f35,0x3ec4bf6d,
0x3f800000,0xbf6d3ec4,0xbf800000,0x3f6dbec4,0x3f35bf35,0xbec43f6d,0xbf353f35,0x3ec4bf6d,0xbf80,0x3ec43f6d,0x3f80,0xbec4bf6d,
0xbf35bf35,0x3f6d3ec4,0x3f353f35,0xbf6dbec4,0x80003f80,0xbf6dbec4,0x8000bf80,0x3f6d3ec4,0x3f35bf35,0x3ec43f6d,0xbf353f35,0xbec4bf6d,
0xbf800000,0x3ec4bf6d,0x3f800000,0xbec43f6d,0x3f353f35,0xbf6d3ec4,0xbf35bf35,0x3f6dbec4,0x3f800000,0xbec43f6d,0xbf800000,0x3ec4bf6d,
0xbf35bf35,0x3f6dbec4,0x3f353f35,0xbf6d3ec4,0x3f80,0xbf6dbec4,0xbf80,0x3f6d3ec4,0x3f35bf35,0x3ec43f6d,0xbf353f35,0xbec4bf6d,
0x80003f80,0xbf6d3ec4,0x8000bf80,0x3f6dbec4,0xbf35bf35,0x3ec4bf6d,0x3f353f35,0xbec43f6d,0x3f800000,0x3ec43f6d,0xbf800000,0xbec4bf6d,
0xbf353f35,0xbf6dbec4,0x3f35bf35,0x3f6d3ec4,0x3f800000,0x3ec43f6d,0xbf800000,0xbec4bf6d,0xbf353f35,0xbf6dbec4,0x3f35bf35,0x3f6d3ec4,
0xbf80,0x3f6dbec4,0x3f80,0xbf6d3ec4,0x3f353f35,0xbec43f6d,0xbf35bf35,0x3ec4bf6d,0x80003f80,0xbec43f6d,0x8000bf80,0x3ec4bf6d,
0xbf353f35,0xbf6d3ec4,0x3f35bf35,0x3f6dbec4,0xbf800000,0xbf6dbec4,0x3f800000,0x3f6d3ec4,0xbf35bf35,0xbec4bf6d,0x3f353f35,0x3ec43f6d,
0x3f800000,0x3f6d3ec4,0xbf800000,0xbf6dbec4,0x3f353f35,0x3ec43f6d,0xbf35bf35,0xbec4bf6d,0x3f80,0xbec43f6d,0xbf80,0x3ec4bf6d,
0xbf353f35,0xbf6d3ec4,0x3f35bf35,0x3f6dbec4,
};
constexpr int TB_F = 0, TB_E = 512, TB_P2 = 1024;

enum { C_EP = 0, C_Z1 = 32, C_Z2 = 96, C_H3 = 128, C_U = 160, C_X = 256, C_TOTAL = 512 };
struct Scratch {
  unsigned cnt[C_TOTAL];
  uint32_t moda[8 * 2 * D_];
  uint32_t mod[4 * D_ + 256];
  uint32_t z1[120 * 5120];
  uint32_t z2[128 * 4800];
  uint8_t h3[32 * 18 * 4096];
  uint8_t u[72 * D_ * 128];
};
__device__ __align__(1024) Scratch g_s;

#define PF2 8
#define PF2K 16
#define HOLDA 5
#define GOAT 0
#define HW bulk_commit_wait
#define H3W 0
#define X1K 10
#define PEEK 1
#define H3G 1
#define PFF 2
#ifndef NV1
#define NV1 12
#endif
#ifndef NV2
#define NV2 20
#endif
#define GDEP 0
#define TRK0 50
#define W0N 3
#define TRKC 350
#define J2 6
#define MODPOS 2
#define W2H 1
#define NG1 2

#define FAILCNT(k) do {} while (0)
#define CK(k) do {} while (0)
#define CKX(k) do {} while (0)
#define TS(k) do {} while (0)
#define TSC(k) do {} while (0)
struct Maps { CUtensorMap z1, z2[2], w1a, w1b, h3[2], w2, wf[4], wm; };
struct Params {
  const __nv_bfloat16 *x, *c, *wmod;
  Scratch* s;
  const uint4* tab;
  const __nv_bfloat16 *wr, *wi, *w1, *w2, *b1, *b2;
  uint32_t* out;
};

__device__ __forceinline__ uint32_t smem_u32(const void* p) { return (uint32_t)__cvta_generic_to_shared(p); }
__device__ __forceinline__ void mbar_init(uint32_t b, int c) { asm volatile("mbarrier.init.shared::cta.b64 [%0], %1;" ::"r"(b), "r"(c)); }
__device__ __forceinline__ void mbar_expect(uint32_t b, int bytes) { asm volatile("mbarrier.arrive.expect_tx.shared::cta.b64 _, [%0], %1;" ::"r"(b), "r"(bytes) : "memory"); }
__device__ __forceinline__ void mbar_arrive(uint32_t b) { asm volatile("mbarrier.arrive.shared::cta.b64 _, [%0];" ::"r"(b) : "memory"); }
#define MBAR_WAIT(SEM)                                                                                                         \
  asm volatile("{\n.reg .pred p;\n.reg .u32 it;\nmov.u32 it, 0;\nW:\nmbarrier.try_wait.parity" SEM ".shared::cta.b64 p, [%0], %1;\n" \
               "@p bra.uni D;\nadd.u32 it, it, 1;\nsetp.lt.u32 p, it, 0x400000;\n@p bra.uni W;\ntrap;\nD:\n}" ::"r"(b), "r"(ph) : "memory")
__device__ __forceinline__ void mbar_wait(uint32_t b, int ph) { MBAR_WAIT(""); }
__device__ __forceinline__ uint32_t mbar_test(uint32_t b, int ph) {
  uint32_t ok;
  asm volatile("{\n.reg .pred p;\nmbarrier.test_wait.parity.shared::cta.b64 p, [%1], %2;\nselp.u32 %0, 1, 0, p;\n}\n" : "=r"(ok) : "r"(b), "r"(ph) : "memory");
  return ok;
}
__device__ __forceinline__ void tma2d(uint32_t dst, const CUtensorMap* m, int c0, int c1, uint32_t bar) {
  asm volatile("cp.async.bulk.tensor.2d.shared::cluster.global.mbarrier::complete_tx::bytes [%0], [%1, {%3, %4}], [%2];" ::"r"(dst), "l"(m), "r"(bar), "r"(c0), "r"(c1) : "memory");
}
__device__ __forceinline__ uint64_t pol_ef() { uint64_t p; asm("createpolicy.fractional.L2::evict_first.b64 %0, 1.0;" : "=l"(p)); return p; }
__device__ __forceinline__ void tma3d_ef(uint32_t dst, const CUtensorMap* m, int c1, int c2, uint32_t bar) {
  asm volatile("cp.async.bulk.tensor.3d.shared::cluster.global.mbarrier::complete_tx::bytes.L2::cache_hint [%0], [%1, {%3, %4, %5}], [%2], %6;" ::"r"(dst), "l"(m), "r"(bar), "r"(0), "r"(c1), "r"(c2), "l"(pol_ef()) : "memory");
}
__device__ __forceinline__ void tma4d_ef(uint32_t dst, const CUtensorMap* m, int c1, int c2, int c3, uint32_t bar) {
  asm volatile("cp.async.bulk.tensor.4d.shared::cluster.global.mbarrier::complete_tx::bytes.L2::cache_hint [%0], [%1, {%3, %7, %4, %5}], [%2], %6;" ::"r"(dst), "l"(m), "r"(bar), "r"(0), "r"(c2), "r"(c3), "l"(pol_ef()), "r"(c1) : "memory");
}
__device__ __forceinline__ void bulk_ld(uint32_t dst, const void* src, int bytes, uint32_t bar) {
  asm volatile("cp.async.bulk.shared::cluster.global.mbarrier::complete_tx::bytes [%0], [%1], %2, [%3];" ::"r"(dst), "l"(src), "r"(bytes), "r"(bar) : "memory");
}
__device__ __forceinline__ void bulk_st(void* dst, uint32_t src, int bytes) {
  asm volatile("cp.async.bulk.global.shared::cta.bulk_group [%0], [%1], %2;" ::"l"(dst), "r"(src), "r"(bytes) : "memory");
}
__device__ __forceinline__ void tma_st2d(const CUtensorMap* m, uint32_t src, int c0, int c1) {
  asm volatile("cp.async.bulk.tensor.2d.global.shared::cta.bulk_group [%0, {%2, %3}], [%1];" ::"l"(m), "r"(src), "r"(c0), "r"(c1) : "memory");
}
__device__ __forceinline__ void tma_st3d(const CUtensorMap* m, uint32_t src, int c0, int c1, int c2) {
  asm volatile("cp.async.bulk.tensor.3d.global.shared::cta.bulk_group [%0, {%2, %3, %4}], [%1];" ::"l"(m), "r"(src), "r"(c0), "r"(c1), "r"(c2) : "memory");
}
__device__ __forceinline__ void bulk_commit_wait_read() {
  asm volatile("cp.async.bulk.commit_group;" ::: "memory");
  asm volatile("cp.async.bulk.wait_group.read 0;" ::: "memory");
}
__device__ __forceinline__ void bulk_commit_wait() {
  asm volatile("cp.async.bulk.commit_group;" ::: "memory");
  asm volatile("cp.async.bulk.wait_group 0;" ::: "memory");
}
__device__ __forceinline__ void prefetch_l2(const void* p, int bytes) {
  asm volatile("cp.async.bulk.prefetch.L2.global [%0], %1;" ::"l"(p), "r"(bytes) : "memory");
}
__device__ __forceinline__ void wg_fence() { asm volatile("wgmma.fence.sync.aligned;" ::: "memory"); }
__device__ __forceinline__ void wg_commit() { asm volatile("wgmma.commit_group.sync.aligned;" ::: "memory"); }
template <int N> __device__ __forceinline__ void wg_wait() { asm volatile("wgmma.wait_group.sync.aligned %0;" ::"n"(N) : "memory"); }
template <int N> __device__ __forceinline__ void reg_fence(float (&d)[N]) {
#pragma unroll
  for (int i = 0; i < N; i++) asm volatile("" : "+f"(d[i])::"memory");
}
__device__ __forceinline__ void fence_async_smem() { asm volatile("fence.proxy.async.shared::cta;" ::: "memory"); }
__device__ __forceinline__ void fence_async_glb() { asm volatile("fence.proxy.async.global;" ::: "memory"); }
__device__ __forceinline__ uint32_t ld_rlx(const void* p) { uint32_t v; asm volatile("ld.relaxed.gpu.global.b32 %0, [%1];" : "=r"(v) : "l"(p) : "memory"); return v; }
__device__ __forceinline__ uint2 ld_rlx2(const void* p) { uint2 v; asm volatile("ld.relaxed.gpu.global.v2.b32 {%0,%1}, [%2];" : "=r"(v.x), "=r"(v.y) : "l"(p) : "memory"); return v; }
__device__ __forceinline__ uint4 ld_rlx4(const void* p) { uint4 v; asm volatile("ld.relaxed.gpu.global.v4.b32 {%0,%1,%2,%3}, [%4];" : "=r"(v.x), "=r"(v.y), "=r"(v.z), "=r"(v.w) : "l"(p) : "memory"); return v; }
__device__ __forceinline__ uint32_t ld_nc(const void* p) { uint32_t v; asm volatile("ld.global.nc.L1::no_allocate.b32 %0, [%1];" : "=r"(v) : "l"(p) : "memory"); return v; }
__device__ __forceinline__ uint4 ld_nc4(const void* p) { uint4 v; asm volatile("ld.global.nc.v4.b32 {%0,%1,%2,%3}, [%4];" : "=r"(v.x), "=r"(v.y), "=r"(v.z), "=r"(v.w) : "l"(p) : "memory"); return v; }
__device__ __forceinline__ uint32_t lds(uint32_t a) { uint32_t v; asm volatile("ld.shared.b32 %0, [%1];" : "=r"(v) : "r"(a) : "memory"); return v; }
__device__ __forceinline__ uint2 lds2(uint32_t a) { uint2 v; asm volatile("ld.shared.v2.b32 {%0,%1}, [%2];" : "=r"(v.x), "=r"(v.y) : "r"(a) : "memory"); return v; }
__device__ __forceinline__ uint4 lds4(uint32_t a) { uint4 v; asm volatile("ld.shared.v4.b32 {%0,%1,%2,%3}, [%4];" : "=r"(v.x), "=r"(v.y), "=r"(v.z), "=r"(v.w) : "r"(a) : "memory"); return v; }
__device__ __forceinline__ float lds_bf(uint32_t a) { uint32_t v; asm volatile("ld.shared.u16 %0, [%1];" : "=r"(v) : "r"(a) : "memory"); return __uint_as_float(v << 16); }
__device__ __forceinline__ void sts(uint32_t a, uint32_t v) { asm volatile("st.shared.b32 [%0], %1;" ::"r"(a), "r"(v) : "memory"); }
__device__ __forceinline__ void sts2(uint32_t a, uint32_t v0, uint32_t v1) { asm volatile("st.shared.v2.b32 [%0], {%1,%2};" ::"r"(a), "r"(v0), "r"(v1) : "memory"); }
__device__ __forceinline__ void sts4(uint32_t a, uint32_t v0, uint32_t v1, uint32_t v2, uint32_t v3) { asm volatile("st.shared.v4.b32 [%0], {%1,%2,%3,%4};" ::"r"(a), "r"(v0), "r"(v1), "r"(v2), "r"(v3) : "memory"); }
__device__ __forceinline__ void bar_sync(int id, int n) { asm volatile("bar.sync %0, %1;" ::"r"(id), "r"(n) : "memory"); }
__device__ __forceinline__ void bar_arrive(int id, int n) { asm volatile("bar.arrive %0, %1;" ::"r"(id), "r"(n) : "memory"); }
__device__ __forceinline__ void red_add(unsigned* p, unsigned v) { asm volatile("red.relaxed.gpu.global.add.u32 [%0], %1;" ::"l"(p), "r"(v) : "memory"); }
__device__ __forceinline__ bool any(bool p) { return __any_sync(0xffffffffu, p); }
__device__ __forceinline__ void pause(unsigned clks) {
  asm volatile("{\n.reg .pred p;\n.reg .u32 a, b;\nmov.u32 a, %%clock;\nW:\nmov.u32 b, %%clock;\nsub.u32 b, b, a;\nsetp.lt.s32 p, b, %0;\n@p bra.uni W;\n}" ::"r"(clks) : "memory");
}
__device__ __forceinline__ void red_bf16x8(uint32_t* p, uint32_t a, uint32_t b, uint32_t c, uint32_t d) {
  asm volatile("red.relaxed.gpu.global.add.noftz.v4.bf16x2 [%0], {%1,%2,%3,%4};" ::"l"(p), "r"(a), "r"(b), "r"(c), "r"(d) : "memory");
}
__device__ __forceinline__ void red_bf16x4(uint32_t* p, uint32_t a, uint32_t b) {
  asm volatile("red.relaxed.gpu.global.add.noftz.v2.bf16x2 [%0], {%1,%2};" ::"l"(p), "r"(a), "r"(b) : "memory");
}
constexpr int SPIN_MAX = 1 << 20;
__device__ __forceinline__ uint32_t ld_acq(const void* p) { uint32_t v; asm volatile("ld.acquire.gpu.global.b32 %0, [%1];" : "=r"(v) : "l"(p) : "memory"); return v; }
template <bool ACQ = false> __device__ __forceinline__ void wait_cnt(const unsigned* p, unsigned target) {
  int it = 0;
  while (any((int)((ACQ ? ld_acq(p) : ld_rlx(p)) - target) < 0) && ++it < SPIN_MAX) {}
}
__device__ __forceinline__ uint32_t pack_bf16(float lo, float hi) { uint32_t r; asm("cvt.rn.bf16x2.f32 %0, %1, %2;" : "=r"(r) : "f"(hi), "f"(lo)); return r; }
__device__ __forceinline__ float bf_lo(uint32_t v) { return __uint_as_float(v << 16); }
__device__ __forceinline__ float bf_hi(uint32_t v) { return __uint_as_float(v & 0xffff0000u); }
__device__ __forceinline__ uint32_t hadd2(uint32_t a, uint32_t b) { uint32_t r; asm("add.rn.bf16x2 %0, %1, %2;" : "=r"(r) : "r"(a), "r"(b)); return r; }
__device__ __forceinline__ uint32_t hmul2(uint32_t a, uint32_t b) { uint32_t r; asm("mul.rn.bf16x2 %0, %1, %2;" : "=r"(r) : "r"(a), "r"(b)); return r; }
__device__ __forceinline__ uint32_t hfma2(uint32_t a, uint32_t b, uint32_t c) { uint32_t r; asm("fma.rn.bf16x2 %0, %1, %2, %3;" : "=r"(r) : "r"(a), "r"(b), "r"(c)); return r; }
__device__ __forceinline__ float rbf(float x) { uint32_t r; asm("cvt.rn.bf16x2.f32 %0, %1, %2;" : "=r"(r) : "f"(x), "f"(0.0f)); return __uint_as_float(r); }
__device__ __forceinline__ void stmatrix4(uint32_t a, uint32_t r0, uint32_t r1, uint32_t r2, uint32_t r3) {
  asm volatile("stmatrix.sync.aligned.m8n8.x4.shared.b16 [%0], {%1,%2,%3,%4};" ::"r"(a), "r"(r0), "r"(r1), "r"(r2), "r"(r3) : "memory");
}
__device__ __forceinline__ void stmatrix2(uint32_t a, uint32_t r0, uint32_t r1) {
  asm volatile("stmatrix.sync.aligned.m8n8.x2.shared.b16 [%0], {%1,%2};" ::"r"(a), "r"(r0), "r"(r1) : "memory");
}
__device__ __forceinline__ void stmatrix4t(uint32_t a, uint32_t r0, uint32_t r1, uint32_t r2, uint32_t r3) {
  asm volatile("stmatrix.sync.aligned.m8n8.x4.trans.shared.b16 [%0], {%1,%2,%3,%4};" ::"r"(a), "r"(r0), "r"(r1), "r"(r2), "r"(r3) : "memory");
}
__device__ __forceinline__ uint32_t movm(uint32_t a) { uint32_t r; asm("movmatrix.sync.aligned.m8n8.trans.b16 %0, %1;" : "=r"(r) : "r"(a)); return r; }
template <bool ACC> __device__ __forceinline__ void mma16(float* d, uint32_t a0, uint32_t a1, uint32_t a2, uint32_t a3, uint32_t b0, uint32_t b1) {
  if (ACC) asm("mma.sync.aligned.m16n8k16.row.col.f32.bf16.bf16.f32 {%0,%1,%2,%3}, {%4,%5,%6,%7}, {%8,%9}, {%0,%1,%2,%3};"
               : "+f"(d[0]), "+f"(d[1]), "+f"(d[2]), "+f"(d[3]) : "r"(a0), "r"(a1), "r"(a2), "r"(a3), "r"(b0), "r"(b1));
  else asm("mma.sync.aligned.m16n8k16.row.col.f32.bf16.bf16.f32 {%0,%1,%2,%3}, {%4,%5,%6,%7}, {%8,%9}, {%10,%10,%10,%10};"
           : "=f"(d[0]), "=f"(d[1]), "=f"(d[2]), "=f"(d[3]) : "r"(a0), "r"(a1), "r"(a2), "r"(a3), "r"(b0), "r"(b1), "f"(0.f));
}
__device__ __forceinline__ uint32_t pin(uint32_t v) { uint32_t r; asm volatile("shfl.sync.bfly.b32 %0, %1, 0, 31, 0xffffffff;" : "=r"(r) : "r"(v)); return r; }
template <class T> __device__ __forceinline__ T* pin(T* p) {
  const uint64_t a = reinterpret_cast<uint64_t>(p);
  return reinterpret_cast<T*>((uint64_t)pin((uint32_t)a) | ((uint64_t)pin((uint32_t)(a >> 32)) << 32));
}
__device__ __forceinline__ uint32_t upin(uint32_t v) { return __shfl_sync(0xffffffffu, v, 0); }
template <class T> __device__ __forceinline__ T* upin(T* p) {
  const uint64_t a = reinterpret_cast<uint64_t>(p);
  return reinterpret_cast<T*>((uint64_t)upin((uint32_t)a) | ((uint64_t)upin((uint32_t)(a >> 32)) << 32));
}
__device__ __forceinline__ bool elect() {
  uint32_t p;
  asm volatile("{\n.reg .pred P;\nelect.sync _|P, 0xffffffff;\nselp.u32 %0, 1, 0, P;\n}" : "=r"(p));
  return p;
}
__device__ __forceinline__ uint32_t set_tag(uint32_t w, uint32_t tag) { uint32_t r; asm("lop3.b32 %0, %1, 0xfffffffe, %2, 0xea;" : "=r"(r) : "r"(w), "r"(tag)); return r; }
__device__ __forceinline__ uint32_t bitsel(uint32_t w, uint32_t m, uint32_t o) { uint32_t r; asm("lop3.b32 %0, %1, %2, %3, 0xe2;" : "=r"(r) : "r"(w), "r"(m), "r"(o)); return r; }
__device__ __forceinline__ uint32_t or3(uint32_t a, uint32_t b, uint32_t c) { uint32_t r; asm("lop3.b32 %0, %1, %2, %3, 0xfe;" : "=r"(r) : "r"(a), "r"(b), "r"(c)); return r; }
__device__ __forceinline__ uint32_t diff2(uint32_t a, uint32_t b, uint32_t tag) { uint32_t r; asm("lop3.b32 %0, %1, %2, %3, 0x7e;" : "=r"(r) : "r"(a), "r"(b), "r"(tag)); return r; }
__device__ __forceinline__ float2 cmul(float2 a, float2 b) { return make_float2(a.x * b.x - a.y * b.y, a.x * b.y + a.y * b.x); }

template<int TB> __device__ __forceinline__ void wgmma_ss_160_0(float (&d)[96], uint32_t al, uint32_t ah, uint32_t bl, uint32_t bh) {
  asm volatile("{\n.reg .b64 da, db;\nmov.b64 da, {%80, %81};\nmov.b64 db, {%82, %83};\n"
    "wgmma.mma_async.sync.aligned.m64n160k16.f32.bf16.bf16 {%0,%1,%2,%3,%4,%5,%6,%7,%8,%9,%10,%11,%12,%13,%14,%15,%16,%17,%18,%19,%20,%21,%22,%23,%24,%25,%26,%27,%28,%29,%30,%31,%32,%33,%34,%35,%36,%37,%38,%39,%40,%41,%42,%43,%44,%45,%46,%47,%48,%49,%50,%51,%52,%53,%54,%55,%56,%57,%58,%59,%60,%61,%62,%63,%64,%65,%66,%67,%68,%69,%70,%71,%72,%73,%74,%75,%76,%77,%78,%79}, da, db, 1, 1, 1, 1, %84;\n}\n"
    : "+f"(d[0]),"+f"(d[1]),"+f"(d[2]),"+f"(d[3]),"+f"(d[4]),"+f"(d[5]),"+f"(d[6]),"+f"(d[7]),"+f"(d[8]),"+f"(d[9]),"+f"(d[10]),"+f"(d[11]),"+f"(d[12]),"+f"(d[13]),"+f"(d[14]),"+f"(d[15]),"+f"(d[16]),"+f"(d[17]),"+f"(d[18]),"+f"(d[19]),"+f"(d[20]),"+f"(d[21]),"+f"(d[22]),"+f"(d[23]),"+f"(d[24]),"+f"(d[25]),"+f"(d[26]),"+f"(d[27]),"+f"(d[28]),"+f"(d[29]),"+f"(d[30]),"+f"(d[31]),"+f"(d[32]),"+f"(d[33]),"+f"(d[34]),"+f"(d[35]),"+f"(d[36]),"+f"(d[37]),"+f"(d[38]),"+f"(d[39]),"+f"(d[40]),"+f"(d[41]),"+f"(d[42]),"+f"(d[43]),"+f"(d[44]),"+f"(d[45]),"+f"(d[46]),"+f"(d[47]),"+f"(d[48]),"+f"(d[49]),"+f"(d[50]),"+f"(d[51]),"+f"(d[52]),"+f"(d[53]),"+f"(d[54]),"+f"(d[55]),"+f"(d[56]),"+f"(d[57]),"+f"(d[58]),"+f"(d[59]),"+f"(d[60]),"+f"(d[61]),"+f"(d[62]),"+f"(d[63]),"+f"(d[64]),"+f"(d[65]),"+f"(d[66]),"+f"(d[67]),"+f"(d[68]),"+f"(d[69]),"+f"(d[70]),"+f"(d[71]),"+f"(d[72]),"+f"(d[73]),"+f"(d[74]),"+f"(d[75]),"+f"(d[76]),"+f"(d[77]),"+f"(d[78]),"+f"(d[79])
    : "r"(al), "r"(ah), "r"(bl), "r"(bh), "n"(TB));
}
template<int TB> __device__ __forceinline__ void wgmma_ss_144_0(float (&d)[96], uint32_t al, uint32_t ah, uint32_t bl, uint32_t bh) {
  asm volatile("{\n.reg .b64 da, db;\nmov.b64 da, {%72, %73};\nmov.b64 db, {%74, %75};\n"
    "wgmma.mma_async.sync.aligned.m64n144k16.f32.bf16.bf16 {%0,%1,%2,%3,%4,%5,%6,%7,%8,%9,%10,%11,%12,%13,%14,%15,%16,%17,%18,%19,%20,%21,%22,%23,%24,%25,%26,%27,%28,%29,%30,%31,%32,%33,%34,%35,%36,%37,%38,%39,%40,%41,%42,%43,%44,%45,%46,%47,%48,%49,%50,%51,%52,%53,%54,%55,%56,%57,%58,%59,%60,%61,%62,%63,%64,%65,%66,%67,%68,%69,%70,%71}, da, db, 1, 1, 1, 1, %76;\n}\n"
    : "+f"(d[0]),"+f"(d[1]),"+f"(d[2]),"+f"(d[3]),"+f"(d[4]),"+f"(d[5]),"+f"(d[6]),"+f"(d[7]),"+f"(d[8]),"+f"(d[9]),"+f"(d[10]),"+f"(d[11]),"+f"(d[12]),"+f"(d[13]),"+f"(d[14]),"+f"(d[15]),"+f"(d[16]),"+f"(d[17]),"+f"(d[18]),"+f"(d[19]),"+f"(d[20]),"+f"(d[21]),"+f"(d[22]),"+f"(d[23]),"+f"(d[24]),"+f"(d[25]),"+f"(d[26]),"+f"(d[27]),"+f"(d[28]),"+f"(d[29]),"+f"(d[30]),"+f"(d[31]),"+f"(d[32]),"+f"(d[33]),"+f"(d[34]),"+f"(d[35]),"+f"(d[36]),"+f"(d[37]),"+f"(d[38]),"+f"(d[39]),"+f"(d[40]),"+f"(d[41]),"+f"(d[42]),"+f"(d[43]),"+f"(d[44]),"+f"(d[45]),"+f"(d[46]),"+f"(d[47]),"+f"(d[48]),"+f"(d[49]),"+f"(d[50]),"+f"(d[51]),"+f"(d[52]),"+f"(d[53]),"+f"(d[54]),"+f"(d[55]),"+f"(d[56]),"+f"(d[57]),"+f"(d[58]),"+f"(d[59]),"+f"(d[60]),"+f"(d[61]),"+f"(d[62]),"+f"(d[63]),"+f"(d[64]),"+f"(d[65]),"+f"(d[66]),"+f"(d[67]),"+f"(d[68]),"+f"(d[69]),"+f"(d[70]),"+f"(d[71])
    : "r"(al), "r"(ah), "r"(bl), "r"(bh), "n"(TB));
}
template<int TB> __device__ __forceinline__ void wgmma_ss_96_0(float (&d)[96], uint32_t al, uint32_t ah, uint32_t bl, uint32_t bh) {
  asm volatile("{\n.reg .b64 da, db;\nmov.b64 da, {%48, %49};\nmov.b64 db, {%50, %51};\n"
    "wgmma.mma_async.sync.aligned.m64n96k16.f32.bf16.bf16 {%0,%1,%2,%3,%4,%5,%6,%7,%8,%9,%10,%11,%12,%13,%14,%15,%16,%17,%18,%19,%20,%21,%22,%23,%24,%25,%26,%27,%28,%29,%30,%31,%32,%33,%34,%35,%36,%37,%38,%39,%40,%41,%42,%43,%44,%45,%46,%47}, da, db, 1, 1, 1, 1, %52;\n}\n"
    : "+f"(d[0]),"+f"(d[1]),"+f"(d[2]),"+f"(d[3]),"+f"(d[4]),"+f"(d[5]),"+f"(d[6]),"+f"(d[7]),"+f"(d[8]),"+f"(d[9]),"+f"(d[10]),"+f"(d[11]),"+f"(d[12]),"+f"(d[13]),"+f"(d[14]),"+f"(d[15]),"+f"(d[16]),"+f"(d[17]),"+f"(d[18]),"+f"(d[19]),"+f"(d[20]),"+f"(d[21]),"+f"(d[22]),"+f"(d[23]),"+f"(d[24]),"+f"(d[25]),"+f"(d[26]),"+f"(d[27]),"+f"(d[28]),"+f"(d[29]),"+f"(d[30]),"+f"(d[31]),"+f"(d[32]),"+f"(d[33]),"+f"(d[34]),"+f"(d[35]),"+f"(d[36]),"+f"(d[37]),"+f"(d[38]),"+f"(d[39]),"+f"(d[40]),"+f"(d[41]),"+f"(d[42]),"+f"(d[43]),"+f"(d[44]),"+f"(d[45]),"+f"(d[46]),"+f"(d[47])
    : "r"(al), "r"(ah), "r"(bl), "r"(bh), "n"(TB));
}
template<int TB> __device__ __forceinline__ void wgmma_ss_96_48(float (&d)[96], uint32_t al, uint32_t ah, uint32_t bl, uint32_t bh) {
  asm volatile("{\n.reg .b64 da, db;\nmov.b64 da, {%48, %49};\nmov.b64 db, {%50, %51};\n"
    "wgmma.mma_async.sync.aligned.m64n96k16.f32.bf16.bf16 {%0,%1,%2,%3,%4,%5,%6,%7,%8,%9,%10,%11,%12,%13,%14,%15,%16,%17,%18,%19,%20,%21,%22,%23,%24,%25,%26,%27,%28,%29,%30,%31,%32,%33,%34,%35,%36,%37,%38,%39,%40,%41,%42,%43,%44,%45,%46,%47}, da, db, 1, 1, 1, 1, %52;\n}\n"
    : "+f"(d[48]),"+f"(d[49]),"+f"(d[50]),"+f"(d[51]),"+f"(d[52]),"+f"(d[53]),"+f"(d[54]),"+f"(d[55]),"+f"(d[56]),"+f"(d[57]),"+f"(d[58]),"+f"(d[59]),"+f"(d[60]),"+f"(d[61]),"+f"(d[62]),"+f"(d[63]),"+f"(d[64]),"+f"(d[65]),"+f"(d[66]),"+f"(d[67]),"+f"(d[68]),"+f"(d[69]),"+f"(d[70]),"+f"(d[71]),"+f"(d[72]),"+f"(d[73]),"+f"(d[74]),"+f"(d[75]),"+f"(d[76]),"+f"(d[77]),"+f"(d[78]),"+f"(d[79]),"+f"(d[80]),"+f"(d[81]),"+f"(d[82]),"+f"(d[83]),"+f"(d[84]),"+f"(d[85]),"+f"(d[86]),"+f"(d[87]),"+f"(d[88]),"+f"(d[89]),"+f"(d[90]),"+f"(d[91]),"+f"(d[92]),"+f"(d[93]),"+f"(d[94]),"+f"(d[95])
    : "r"(al), "r"(ah), "r"(bl), "r"(bh), "n"(TB));
}
__device__ __forceinline__ void wgmma_rs_72(float (&d)[36], uint32_t a0, uint32_t a1, uint32_t a2, uint32_t a3, uint32_t bl, uint32_t bh, int sd) {
  asm volatile("{\n.reg .pred p;\n.reg .b64 db;\nsetp.ne.b32 p, %42, 0;\nmov.b64 db, {%40, %41};\n"
    "wgmma.mma_async.sync.aligned.m64n72k16.f32.bf16.bf16 {%0,%1,%2,%3,%4,%5,%6,%7,%8,%9,%10,%11,%12,%13,%14,%15,%16,%17,%18,%19,%20,%21,%22,%23,%24,%25,%26,%27,%28,%29,%30,%31,%32,%33,%34,%35}, {%36,%37,%38,%39}, db, p, 1, 1, 1;\n}\n"
    : "+f"(d[0]),"+f"(d[1]),"+f"(d[2]),"+f"(d[3]),"+f"(d[4]),"+f"(d[5]),"+f"(d[6]),"+f"(d[7]),"+f"(d[8]),"+f"(d[9]),"+f"(d[10]),"+f"(d[11]),"+f"(d[12]),"+f"(d[13]),"+f"(d[14]),"+f"(d[15]),"+f"(d[16]),"+f"(d[17]),"+f"(d[18]),"+f"(d[19]),"+f"(d[20]),"+f"(d[21]),"+f"(d[22]),"+f"(d[23]),"+f"(d[24]),"+f"(d[25]),"+f"(d[26]),"+f"(d[27]),"+f"(d[28]),"+f"(d[29]),"+f"(d[30]),"+f"(d[31]),"+f"(d[32]),"+f"(d[33]),"+f"(d[34]),"+f"(d[35])
    : "r"(a0), "r"(a1), "r"(a2), "r"(a3), "r"(bl), "r"(bh), "r"(sd));
}
__device__ __forceinline__ void wgmma_rs_48(float (&d)[24], uint32_t a0, uint32_t a1, uint32_t a2, uint32_t a3, uint32_t bl, uint32_t bh, int sd) {
  asm volatile("{\n.reg .pred p;\n.reg .b64 db;\nsetp.ne.b32 p, %30, 0;\nmov.b64 db, {%28, %29};\n"
    "wgmma.mma_async.sync.aligned.m64n48k16.f32.bf16.bf16 {%0,%1,%2,%3,%4,%5,%6,%7,%8,%9,%10,%11,%12,%13,%14,%15,%16,%17,%18,%19,%20,%21,%22,%23}, {%24,%25,%26,%27}, db, p, 1, 1, 1;\n}\n"
    : "+f"(d[0]),"+f"(d[1]),"+f"(d[2]),"+f"(d[3]),"+f"(d[4]),"+f"(d[5]),"+f"(d[6]),"+f"(d[7]),"+f"(d[8]),"+f"(d[9]),"+f"(d[10]),"+f"(d[11]),"+f"(d[12]),"+f"(d[13]),"+f"(d[14]),"+f"(d[15]),"+f"(d[16]),"+f"(d[17]),"+f"(d[18]),"+f"(d[19]),"+f"(d[20]),"+f"(d[21]),"+f"(d[22]),"+f"(d[23])
    : "r"(a0), "r"(a1), "r"(a2), "r"(a3), "r"(bl), "r"(bh), "r"(sd));
}
template<int N,int OFF,int TB> __device__ __forceinline__ void wgmma_ss(float (&d)[96], uint32_t al, uint32_t ah, uint32_t bl, uint32_t bh) {
  if constexpr (N==160 && OFF==0) wgmma_ss_160_0<TB>(d, al, ah, bl, bh);
  else if constexpr (N==144 && OFF==0) wgmma_ss_144_0<TB>(d, al, ah, bl, bh);
  else if constexpr (N==96 && OFF==0) wgmma_ss_96_0<TB>(d, al, ah, bl, bh);
  else if constexpr (N==96 && OFF==48) wgmma_ss_96_48<TB>(d, al, ah, bl, bh);
}

__device__ __forceinline__ void dft3(float2& a, float2& b, float2& c) {
  const float s = 0.86602540378443864676f;
  float2 t = make_float2(b.x + c.x, b.y + c.y), d = make_float2(b.x - c.x, b.y - c.y);
  float2 m = make_float2(fmaf(-0.5f, t.x, a.x), fmaf(-0.5f, t.y, a.y));
  a = make_float2(a.x + t.x, a.y + t.y);
  b = make_float2(fmaf(s, d.y, m.x), fmaf(-s, d.x, m.y));
  c = make_float2(fmaf(-s, d.y, m.x), fmaf(s, d.x, m.y));
}
__device__ __forceinline__ void dft9(float2 (&x)[9]) {
  const float2 w1 = make_float2(0.76604444311897803520f, -0.64278760968653932632f);
  const float2 w2 = make_float2(0.17364817766693034885f, -0.98480775301220805937f);
  const float2 w4 = make_float2(-0.93969262078590838405f, -0.34202014332566873304f);
  dft3(x[0], x[3], x[6]); dft3(x[1], x[4], x[7]); dft3(x[2], x[5], x[8]);
  x[4] = cmul(x[4], w1); x[7] = cmul(x[7], w2); x[5] = cmul(x[5], w2); x[8] = cmul(x[8], w4);
  dft3(x[0], x[1], x[2]); dft3(x[3], x[4], x[5]); dft3(x[6], x[7], x[8]);
  float2 t;
  t = x[1]; x[1] = x[3]; x[3] = t;
  t = x[2]; x[2] = x[6]; x[6] = t;
  t = x[5]; x[5] = x[7]; x[7] = t;
}

__device__ __forceinline__ uint32_t* mod_ptr(Scratch* sc, int u, int t128) {
  const int i = t128 & 15;
  return u < 72 ? sc->moda + (t128 >> 4) * (2 * D_) + 16 * u + 2 * (i & 7) + (i >> 3) : sc->mod + 16 * (u - 72) + i;
}
__device__ __forceinline__ void mod_unit(Scratch* sc, int u, int t128, uint32_t sw_, uint32_t bar, int ph, uint32_t rb, uint32_t tag) {
  const int w = t128 >> 5, l = t128 & 31;
  uint32_t b[18];
#pragma unroll
  for (int i = 0; i < 18; i++) b[i] = lds(red + 512 + (72 * w + 4 * i + (l & 3)) * 4);
  const uint32_t sa = pin(sw_ + (144 * w + (l & 7) + 8 * (l >> 4)) * 32 + (((l >> 3) ^ (l >> 2)) & 1) * 16);
  const uint32_t sr = pin(rb + (l >> 2) * 16 + w * 4);
  uint32_t* const dst = pin(mod_ptr(sc, u, t128));
  const int kind = u / 36;
  const float mul = __uint_as_float(pin(__float_as_uint(kind == 0 ? 16.0f : 1.0f))), add = __uint_as_float(pin(__float_as_uint(kind == 1 || kind == 4 ? 1.0f : 0.0f)));
  mbar_wait(bar, ph);
  if (t128 == 0 && u < 72) TS(10);
  float d[3][4];
#pragma unroll
  for (int i = 0; i < 9; i++) {
    uint32_t a0, a1, a2, a3;
    asm volatile("ldmatrix.sync.aligned.m8n8.x4.trans.shared.b16 {%0,%1,%2,%3}, [%4];" : "=r"(a0), "=r"(a1), "=r"(a2), "=r"(a3) : "r"(sa + i * 512) : "memory");
    if (i < 3) mma16<false>(d[i], a0, a1, a2, a3, b[2 * i], b[2 * i + 1]);
    else mma16<true>(d[i % 3], a0, a1, a2, a3, b[2 * i], b[2 * i + 1]);
  }
  if ((l & 3) == 0) { sts(sr, __float_as_uint(d[0][0] + d[1][0] + d[2][0])); sts(sr + 128, __float_as_uint(d[0][2] + d[1][2] + d[2][2])); }
  bar_sync(4, 128);
  const uint4 v = lds4(rb + (l & 15) * 16);
  const float m = rbf(fmaf(rbf((__uint_as_float(v.x) + __uint_as_float(v.y)) + (__uint_as_float(v.z) + __uint_as_float(v.w))), mul, add));
  if (u < 72 || t128 < 16) *dst = __float_as_uint(m) | tag;
}

__device__ __forceinline__ float rsq(float x) { float r; asm("rsqrt.approx.ftz.f32 %0, %1;" : "=f"(r) : "f"(x)); return r; }
__device__ __forceinline__ void ln_stats2(const float (&a)[18], const float (&b)[18], float sc, float& oa, float& ra, float& ob, float& rb) {
  float v[4] = {0.f, 0.f, 0.f, 0.f}, w[4] = {0.f, 0.f, 0.f, 0.f};
#pragma unroll
  for (int i = 0; i < 18; i += 2) {
    v[0] += a[i]; v[1] = fmaf(a[i], a[i], v[1]); v[2] += b[i]; v[3] = fmaf(b[i], b[i], v[3]);
    w[0] += a[i + 1]; w[1] = fmaf(a[i + 1], a[i + 1], w[1]); w[2] += b[i + 1]; w[3] = fmaf(b[i + 1], b[i + 1], w[3]);
  }
#pragma unroll
  for (int e = 0; e < 4; e++) v[e] += w[e];
#pragma unroll
  for (int o = 16; o; o >>= 1) {
#pragma unroll
    for (int e = 0; e < 4; e++) v[e] += __shfl_xor_sync(0xffffffffu, v[e], o);
  }
  const float ma = v[0] * (1.0f / D_), mb = v[2] * (1.0f / D_);
  ra = sc * rsq(fmaxf(fmaf(-ma, ma, v[1] * (1.0f / D_)), 0.f) + 1e-5f);
  rb = sc * rsq(fmaxf(fmaf(-mb, mb, v[3] * (1.0f / D_)), 0.f) + 1e-5f);
  oa = -ma * ra; ob = -mb * rb;
}

__device__ __forceinline__ float tmat(int c, int q, int j) {
  const int ph = q == 1 ? 1024 * j : (q >> 1) * (c + 128 * j) + 512 * (q & 1);
  return __cosf((float)(((ph + 1024) & 2047) - 1024) * (6.283185307179586f / 2048.0f));
}
__device__ __forceinline__ uint32_t line_off(int k1, int kap, int pi, int f) {
  int kd = 64 * k1 + 9 * kap;
  if (kap == 0 && k1 > 4) kd -= 288;
  if (kd >= D_) kd -= D_;
  return pi * 2400 + ((min(kd, D_ - kd) ^ f) << 3);
}

constexpr int JSK = 5;
struct Ring { uint32_t st, ph; };
template <bool G2, class T> __device__ __forceinline__ void ring_next(T& st, T& ph) {
  if (++st == NST) st = 0;
  ph ^= ((G2 ? 0xDu : 0x1u) >> st) & 1;
}
__device__ __forceinline__ void arrive_if(uint32_t a, uint32_t p) {
  asm volatile("{\n.reg .pred p;\nsetp.ne.u32 p, %1, 0;\n@p mbarrier.arrive.shared::cta.b64 _, [%0];\n}" ::"r"(a), "r"(p) : "memory");
}
template <int NA> __device__ __forceinline__ void reg_fence_n(float (&d)[96]) {
#pragma unroll
  for (int i = 0; i < NA; i++) asm volatile("" : "+f"(d[i])::"memory");
}
template <int MODE>
__device__ __forceinline__ void gemm_main(float (&acc)[96], uint32_t da0, uint32_t da1, uint32_t db0, int wg, Ring& rg,
                                          uint32_t* x1p, const uint32_t (&xr)[18]) {
  static_assert(JSK == NST - 1, "the held slot is the first one that is not refilled by GEMM1");
  constexpr int NKB = MODE == 3 ? 36 : 32, J = MODE == 3 ? J2 : JSK;
  constexpr uint32_t HA = 0x40000040u, HB = MODE == 3 ? 0x40000040u : 0x80000020u;
  constexpr uint32_t KA = 2048 >> 4, KB = MODE == 3 ? (32 >> 4) : (1024 >> 4);
  constexpr int NA = MODE == 3 ? 72 : MODE == 1 ? 96 : 80;
  const uint32_t t = threadIdx.x & 127;
  const uint32_t eb = full0 + 8 * NST;
  uint32_t pb = 0, rel = t == 0, prel = 0, ok = 0;
  int n = MODE == 3 ? NKB - J : X1K + 2 * wg;
#pragma unroll 1
  for (int pass = MODE == 3 ? 0 : -1;; pass++) {
#pragma unroll 1
    do {
      const uint32_t so = rg.st * ((MODE == 3 ? STAGE2 : STAGE) >> 4), cb = eb + 8 * rg.st;
      if (__builtin_expect(!ok, 0)) mbar_wait(full0 + 8 * rg.st, rg.ph);
      reg_fence_n<NA>(acc);
      if (MODE == 1 && wg) {
        wg_fence();
#pragma unroll
        for (int k = 0; k < 4; k++) wgmma_ss<96, 48, 1>(acc, da1 + so + k * KA, HA, db0 + so + k * KB, HB);
        wg_commit();
      }
      wg_fence();
#pragma unroll
      for (int k = 0; k < 4; k++) {
        if (k == 3) { ring_next<MODE == 3>(rg.st, rg.ph); ok = PEEK ? mbar_test(full0 + 8 * rg.st, rg.ph) : 0; }
        if (MODE == 0) wgmma_ss<160, 0, 1>(acc, da0 + so + k * KA, HA, db0 + so + k * KB, HB);
        else if (MODE == 3) wgmma_ss<144, 0, 0>(acc, da0 + so + k * KA, HA, db0 + so + k * KB, HB);
        else wgmma_ss<96, 0, 1>(acc, da0 + so + k * KA, HA, db0 + so + k * KB, HB);
      }
      wg_commit();
      wg_wait<1>();
      reg_fence_n<NA>(acc);
      arrive_if(pb, prel);
      pb = cb; prel = rel;
    } while (--n);
    if (pass == 2 - wg) break;
    if (MODE != 3 && pass < 0) {
      if (blockIdx.x < 128) {
#pragma unroll
        for (int i = 0; i < 9; i++) { x1p[32 * i] = xr[i]; x1p[128 * 288 + 32 * i] = xr[9 + i]; }
      }
      n = NKB - JSK - X1K - 2 * wg;
      continue;
    }
    n = 1;
    if (pass == 0) {
      if (MODE != 3) prel = rel & wg;
      else { rel = 0; if (J < NST) prel = 0; }
      n = J - 1 + wg;
      if (!wg) continue;
      wg_wait<0>();
      arrive_if(pb, prel);
      prel = 0;
    }
    bar_sync(1, 256);
  }
  wg_wait<0>();
  reg_fence_n<NA>(acc);
  if (MODE != 3) arrive_if(pb, MODE == 1 ? prel & ~wg : prel);
}

constexpr float GK1 = 2.0f * 0.7978845608028654f, GK3 = 8.0f * 0.044715f * 0.7978845608028654f;

__device__ __forceinline__ int kb2_order(int i) { const int wv = i / 6; return 6 * (i - 6 * wv) + ((0x431250 >> (4 * wv)) & 7); }

__device__ __forceinline__ void wait_flags(const unsigned* base, int n, int idx, unsigned target, uint64_t& ready) {
  if ((ready >> idx) & 1) return;
  const int l = threadIdx.x & 31;
  int it = 0;
  while (true) {
    unsigned a = ld_rlx(base + l), b = l + 32 < n ? ld_rlx(base + l + 32) : target;
    ready = (uint64_t)__ballot_sync(0xffffffffu, (int)(a - target) >= 0) | ((uint64_t)__ballot_sync(0xffffffffu, (int)(b - target) >= 0) << 32);
    if (((ready >> idx) & 1) || ++it > SPIN_MAX) break;
  }
}

enum { B_FULL = 0, B_EMPTY = 6, B_S4 = 12, B_S5, B_LAND, B_FLT = B_LAND + 6, B_Z1, B_Z2, B_GO, B_X, B_WM, B_NUM, B_W0 = B_NUM };

__global__ void __launch_bounds__(NTHR, 1)
fused_kernel(const Params p, const __grid_constant__ Maps maps) {
  extern __shared__ __align__(1024) uint8_t smem_raw[];
  const int tid = threadIdx.x, cta = blockIdx.x, t128 = tid & 127;
  const int wp = __shfl_sync(0xffffffffu, tid >> 5, 0), wg = wp >> 2;
  const int l = tid & 31, g = l >> 2, t = l & 3;
  Scratch* const sc = p.s;
  const bool rows = cta < 128;
  const int R = cta - 12;

  uint32_t xr[18];
  uint32_t cv[3];
  const unsigned ep0 = ld_rlx(&sc->cnt[C_EP]);
  if (tid == 0) TS(0);
  if (wg == 2) {
#pragma unroll
    for (int i = 0; i < 3; i++) cv[i] = ld_nc(reinterpret_cast<const uint32_t*>(p.c) + min(t128 + 128 * i, 287));
    if (wp == 9 && l < 9 && rows) {
      const int h = 9 * cta + l;
      prefetch_l2(reinterpret_cast<const uint8_t*>(p.wmod) + (size_t)(h >> 1) * (12 * D_) + (h & 1) * (2 * D_), 2 * D_);
    }
    if (tid == 256 && cta < 72) {
      mbar_init(full0 + 8 * B_W0, 1);
      fence_async_smem();
      mbar_expect(full0 + 8 * B_W0, 18432);
#pragma unroll 1
      for (int i = 0; i < 3; i++) tma2d(sbase + O_P2 + i * 6144, &maps.wm, 16 * cta, 192 * i, full0 + 8 * B_W0);
    }
    __syncwarp();
#pragma unroll 1
    for (int u = cta < 72 ? cta : 72 + cta; u < 216; u += u < 72 ? 72 : NCTA) if (u < 72 || t128 < 16) *mod_ptr(sc, u, t128) = 0;
    if (wp == 11 && smem_u32(smem_raw) != sbase) __trap();
    if (wp >= 10 && elect()) {
#pragma unroll 1
      for (int i = wp - 10; i < B_NUM; i += 2) mbar_init(full0 + 8 * i, i == B_FLT ? 4 : i == B_WM ? 3 : i < B_LAND ? 2 : 1);
      fence_async_smem();
    }
    __syncwarp();
  }
  CK(0);
  auto load_x = [&]() {
    const uint32_t* xs = reinterpret_cast<const uint32_t*>(p.x) + (size_t)(cta + 256 * wp) * 288 + l;
#pragma unroll
    for (int i = 0; i < 9; i++) { xr[i] = ld_nc(xs + 32 * i); xr[9 + i] = ld_nc(xs + 128 * 288 + 32 * i); }
  };
  if (rows && wg < 2) load_x();
  if (tid == 64 && cta == NCTA - 1) prefetch_l2(p.tab, sizeof(T_TAB));
  __syncwarp();
  auto tag_of = [](unsigned e) { return (e & 0x7fffu) | 0x8000u; };

  if (wg == 2) {
#pragma unroll
    for (int i = 0; i < 3; i++) {
      const float c0 = bf_lo(cv[i]), c1 = bf_hi(cv[i]);
      sts(red + 512 + min(t128 + 128 * i, 287) * 4, pack_bf16(__fdividef(c0, 1.0f + __expf(-c0)), __fdividef(c1, 1.0f + __expf(-c1))));
    }
    if (t128 == 0) sts(full0 + 248, ep0 + 1);
    if (wp == 9 && l < 12) asm volatile("prefetch.tensormap [%0];" ::"l"(&maps.z1 + l) : "memory");
    bar_sync(4, 128);
    if (cta < 72) {
      mod_unit(sc, cta, t128, sbase + O_P2, full0 + 8 * B_W0, 0, red, tag_of(upin(ep0) + 1));
      if (t128 == 0) TS(25);
    }
    CK(1);
  }
  const int pi = R / 15, col0 = 20 * (R - 15 * pi);
  const int xu = DF_ * pi + col0, xv = DF_ * (pi ? 16 - pi : 8) + col0;
  auto load_filter = [&](int a) {
    const int x = (a & 1) ? xv : xu;
    const bool wide = (x & 15) > 12;
    mbar_expect(full0 + 8 * B_FLT, wide ? 12288 : 8192);
    tma2d(sbase + O_RAW + a * 12288, &maps.wf[a & 2], x & ~15, 0, full0 + 8 * B_FLT);
    if (wide) tma2d(sbase + O_RAW + a * 12288 + 8192, &maps.wf[(a & 2) + 1], (x & ~15) + 32, 0, full0 + 8 * B_FLT);
  };
  const int kap = 8 * ((wp & 3) ^ (wg & 1)) + g;
  uint4 af[4];
  if (rows) {
    uint32_t tb[4];
#pragma unroll
    for (int i = 0; i < 4; i++) tb[i] = pack_bf16(tmat(cta, 8 * (i >> 1) + g, 2 * t + 8 * (i & 1)), tmat(cta, 8 * (i >> 1) + g, 2 * t + 8 * (i & 1) + 1));
    uint32_t sb1[3], lo[9];
#pragma unroll
    for (int i = 0; i < 4; i++) tb[i] = pin(tb[i]);
#pragma unroll
    for (int i = 0; i < 3; i++) {
      const int d = 48 * wp + 16 * i + (l & 15);
      sb1[i] = pin(sbase + O_B1 + (l >> 4) * 9216 + (d % 9) * 1024 + (d & 63) * 16);
    }
    const uint32_t snt = pin(sbase + O_NRM + ((l & 7) + 8 * (l >> 4)) * 1168 + (48 * wp + (l & 8)) * 2);
    uint2 ms[3], mc[3];
    const uint32_t smask = pin(t ? 0u : 0xffff0000u);
    const uint32_t* const mp = pin(sc->moda + (cta >> 4) * (2 * D_) + 48 * wp + 2 * g);
    auto load_mod = [&]() {
#pragma unroll
      for (int i = 0; i < 3; i++) { ms[i] = ld_rlx2(mp + 16 * i); mc[i] = ld_rlx2(mp + D_ + 16 * i); }
    };
    if (wg < 2) {
#pragma unroll
      for (int k1 = 0; k1 < 9; k1++) lo[k1] = pin(sbase + O_Z1 + line_off(k1, kap, 4 * wg + t, cta & 3));
      float a[18], b[18];
#pragma unroll
      for (int i = 0; i < 9; i++) { a[2 * i] = bf_lo(xr[i]); a[2 * i + 1] = bf_hi(xr[i]); b[2 * i] = bf_lo(xr[9 + i]); b[2 * i + 1] = bf_hi(xr[9 + i]); }
      float oa, ra, ob, rb;
      ln_stats2(a, b, 1.0f, oa, ra, ob, rb);
      CK(1);
      const uint32_t sn = sbase + O_NRM + wp * 2336 + l * 4;
#pragma unroll
      for (int i = 0; i < 9; i++) {
        sts(sn + i * 128, pack_bf16(fmaf(a[2 * i], ra, oa), fmaf(a[2 * i + 1], ra, oa)));
        sts(sn + 1168 + i * 128, pack_bf16(fmaf(b[2 * i], rb, ob), fmaf(b[2 * i + 1], rb, ob)));
      }
      CK(2);
      bar_arrive(10, NTHR);
      load_mod();
#pragma unroll
      for (int kk = 0; kk < 4; kk++) af[kk] = ld_nc4(p.tab + TB_F + kk * 128 + (t128 ^ (wg << 5)));
      bar_sync(1, 256);
      if (tid == 0) TS(2);
    } else {
      bar_sync(10, NTHR);
      load_mod();
      CK(2);
      if (PFF && wp >= 12 - PFF && elect()) prefetch_l2(reinterpret_cast<const uint8_t*>(wp == 10 ? p.wr : p.wi) + cta * 9248, 9248);
      __syncwarp();
    }
    float rs[3][8];
#pragma unroll
    for (int i = 0; i < 3; i++) {
      uint32_t a0, a1, a2, a3;
      asm volatile("ldmatrix.sync.aligned.m8n8.x4.trans.shared.b16 {%0,%1,%2,%3}, [%4];" : "=r"(a0), "=r"(a1), "=r"(a2), "=r"(a3)
                   : "r"(snt + 32 * i) : "memory");
      mma16<false>(&rs[i][0], a0, a1, a2, a3, tb[0], tb[1]);
      mma16<false>(&rs[i][4], a0, a1, a2, a3, tb[2], tb[3]);
    }
    CK(3);
    const uint32_t tag16 = tag_of(upin(ep0) + 1), tag1 = tag16 & 1;
    {
      int it = 0;
#pragma unroll 1
      while (true) {
        uint32_t bad = 0;
#pragma unroll
        for (int i = 0; i < 3; i++) bad |= diff2(ms[i].x, ms[i].y, tag16) | diff2(mc[i].x, mc[i].y, tag16);
        if (!any(bad & 0xffffu) || ++it > SPIN_MAX) break;
        load_mod();
      }
      CK(4);
      if (tid == 0) TS(3);
#pragma unroll
      for (int i = 0; i < 3; i++) {
        const float c0 = bf_hi(mc[i].x), c1 = bf_hi(mc[i].y);
        const float s0 = __uint_as_float(ms[i].x & smask), s1 = __uint_as_float(ms[i].y & smask);
        stmatrix4(sb1[i], pack_bf16(fmaf(rs[i][0], c0, s0), rs[i][1] * c0), pack_bf16(fmaf(rs[i][2], c1, s1), rs[i][3] * c1),
                  pack_bf16(rs[i][4] * c0, rs[i][5] * c0), pack_bf16(rs[i][6] * c1, rs[i][7] * c1));
      }
    }
    fence_async_smem();
    CK(5);
    if (wg == 2) {
      bar_arrive(5, NTHR);
      if (R >= 0 && elect()) load_filter(wp - 8);
      __syncwarp();
    } else {
      bar_sync(5, NTHR);
      CK(6);
      float acc[36];
      const uint32_t db = (((sbase + O_B1 + wg * 9216) & 0x3FFFF) >> 4) | ((128 >> 4) << 16);
      wg_fence();
#pragma unroll
      for (int kk = 0; kk < 4; kk++) wgmma_rs_72(acc, af[kk].x, af[kk].y, af[kk].z, af[kk].w, db + kk * 16, 1024 >> 4, kk);
      wg_commit();
      wg_wait<0>();
      reg_fence(acc);
      CK(7);
      float2 za[9], zb[9];
#pragma unroll
      for (int i = 0; i < 9; i++) { za[i] = make_float2(acc[4 * i], acc[4 * i + 2]); zb[i] = make_float2(acc[4 * i + 1], acc[4 * i + 3]); }
      dft9(za); dft9(zb);
      if (kap == 0) {
#pragma unroll
        for (int k = 1; k < 5; k++) {
          float2 a = za[k], b = za[9 - k];
          za[k] = make_float2(a.x + b.x, a.y - b.y); za[9 - k] = make_float2(a.y + b.y, b.x - a.x);
          a = zb[k]; b = zb[9 - k];
          zb[k] = make_float2(a.x + b.x, a.y - b.y); zb[9 - k] = make_float2(a.y + b.y, b.x - a.x);
        }
        sts2(lo[0] + 288 * 8, set_tag(pack_bf16(za[0].y, 0.f), tag1), pack_bf16(zb[0].y, 0.f));
        za[0].y = 0.f; zb[0].y = 0.f;
      }
      __syncwarp();
#pragma unroll
      for (int k1 = 0; k1 < 9; k1++) sts2(lo[k1], set_tag(pack_bf16(za[k1].x, za[k1].y), tag1), pack_bf16(zb[k1].x, zb[k1].y));
      fence_async_smem();
      CK(8);
      bar_arrive(2 + wg, 160);
      {
        const uint32_t fx = (((cta >> 4) ^ cta) & 3) << 3, dl = O_IN - O_Z1, st = sbase + O_ST + 15360 + tid * 16;
        sts4(st, (lo[0] ^ fx) + dl, (lo[1] ^ fx) + dl, (lo[2] ^ fx) + dl, (lo[3] ^ fx) + dl);
        sts4(st + 4096, (lo[4] ^ fx) + dl, (lo[5] ^ fx) + dl, (lo[6] ^ fx) + dl, (lo[7] ^ fx) + dl);
        sts4(st + 8192, (lo[8] ^ fx) + dl, (lo[0] ^ fx) + dl + (kap ? 0 : 288 * 8),
             sbase + O_B3 + wg * 1024 + (l >> 4) * 2048 + (2 * (kap & 24) + (l & 15)) * 16, 0);
      }
    }
    {
      uint32_t sy[6];
#pragma unroll
      for (int i = 0; i < 6; i++) {
        const int rr = 16 * (wp & 3) + g + 8 * (i & 1);
        sy[i] = sbase + O_Y + (t * 584 + 64 * ((3 * wg + (i >> 1) + 63 - rr) % 9) + rr) * 4;
      }
      sts4(sbase + O_ST + tid * 16, movm(tb[0]), movm(tb[2]), movm(tb[1]), movm(tb[3]));
      sts4(sbase + O_ST + 6144 + tid * 16, sy[0], sy[1], sy[2], sy[3]);
      sts2(sbase + O_ST + 12288 + tid * 8, sy[4], sy[5]);
    }
  } else {
    __syncthreads();
  }

  const unsigned ep = upin(lds(full0 + 248));
  const uint32_t tag16 = tag_of(ep), tag1 = ep & 1;
  if ((wp >> 1) == 4) {
    if (rows) {
      const int slot = 4 * (cta & 7) + ((cta >> 4) & 3) + 32 * (2 * (cta >> 6) + ((cta >> 3) & 1));
      const uint32_t c0 = upin(40 * slot), c1 = upin(60 * (wp - 8)), src = upin(sbase + O_Z1 + (wp - 8) * 9600);
      const CUtensorMap* mp = upin(&maps.z1);
      unsigned* hint = pin(&sc->cnt[C_Z1 + 32 * (wp - 8)]);
      bar_sync(wp - 6, 160);
      if (elect()) {
        tma_st2d(mp, src, c0, c1);
        HW();
        red_add(hint, 1);
        if (wp == 8) TS(4);
      }
    } else {
      int it = 0;
      while (any((ld_rlx(sc->moda + 36 * l) ^ tag16) & 0xffffu) && ++it < SPIN_MAX) {}
      if (elect()) { load_filter(wp - 8); load_filter(wp - 6); }
    }
    __syncwarp();
  }
  auto load_wm = [&](int u) {
    if (wp > 8 && elect()) {
      mbar_expect(full0 + 8 * B_WM, 6144);
      tma2d(sbase + O_NRM + (wp - 9) * 6144, &maps.wm, 16 * u, 192 * (wp - 9), full0 + 8 * B_WM);
    }
    __syncwarp();
  };
  if (R >= 0) {
    const int nl = (col0 + wp < DF_) + (wg < 2 && col0 + wp + 12 < DF_);
    uint4 cf[2][4], G[4];
#pragma unroll
    for (int i = 0; i < 4; i++) {
      cf[0][i] = __ldg(p.tab + TB_P2 + i * 32 + l);
      cf[1][i] = __ldg(p.tab + TB_P2 + (pi ? i : 4 + i) * 32 + l);
      G[i] = __ldg(p.tab + TB_P2 + (8 + i) * 32 + l);
    }
    const uint32_t* zin = sc->z1 + (size_t)R * 5120;
    if (wp == 10) {
      const uint32_t* zu = upin(zin);
      if (elect()) mbar_expect(full0 + 8 * B_Z1, 20480);
      wait_cnt(&sc->cnt[C_Z1 + 32 * (pi >> 2)], 128 * ep);
      if (elect()) {
        bulk_ld(sbase + O_P2, zu, 20480, full0 + 8 * B_Z1);
        TS(12);
      }
      __syncwarp();
    }
    mbar_wait(full0 + 8 * B_FLT, 0);
    CK(9);
    float wn[16], wc[16];
#pragma unroll 1
    for (int ln = nl - 1; ln >= 0; ln--) {
      const int col = col0 + wp + 12 * ln, k2 = (57 * col) & 63;
      const bool cj = k2 > 32 || (k2 == 32 && col != 288);
      const float nr = ((col & 31) == 0 && col != 0 && col != 288 ? 0.5f : 1.0f) / ((float)S_ * D_), ni = cj ? -nr : nr;
#pragma unroll
      for (int i = 0; i < 16; i++) wn[i] = wc[i];
#pragma unroll
      for (int cl = 0; cl < 2; cl++) {
        const int v = cl ^ (cj && pi), e = ((v ? xv : xu) & 15) + wp + 12 * ln, sh = e < 32 ? 6 : 5;
        const uint32_t base = sbase + O_RAW + v * 12288 + (e < 32 ? 2 * e : 8192 - 64 + 2 * e), msk = e < 32 ? 0x30 : 0x10;
        const int dm = v ? (cj || pi ? -1 : 0) : 0;
#pragma unroll
        for (int tt = 0; tt < 4; tt++) {
          const int kc = g + 64 * (tt >> 1) + 16 * t + 8 * (tt & 1);
          uint32_t a = base + ((((cj ? -kc : kc) + dm) & 127) << sh);
          a ^= (a >> 3) & msk;
          wc[4 * tt + 2 * cl] = lds_bf(a) * nr; wc[4 * tt + 2 * cl + 1] = lds_bf(a + 24576) * ni;
        }
      }
    }
    const float al = __uint_as_float(pin((pi ? 0x3f800000u : 0u) + (l >> 5)));
    const uint32_t tagv = pin(tag1 + (l >> 5));
    CK(10);
    uint32_t off = pin(l * 160 + ((wp ^ (g & 3)) << 3));
    uint32_t offo = pin(sbase + O_P2 + 20480 + off - 64 * l), po = 3072;
    unsigned* hz2 = pin(&sc->cnt[C_Z2]);
    const uint32_t do2 = pin(12288 - 32 * l);
    const CUtensorMap* mz2 = upin(&maps.z2[wp == 0]);
    const uint32_t sz2 = upin(sbase + O_P2 + 20480 + (wp ? 0 : 12288)), cz2 = upin(40 * R + (wp ? 0 : 24));
    mbar_wait(full0 + 8 * B_Z1, 0);
    CK(11);
    if (tid == 0) TS(8);
    if (wg == 2) load_wm(72 + cta);
    uint2 v[4], v2[4];
    const uint32_t o2 = nl > 1 ? 96 : 0;
#pragma unroll
    for (int i = 0; i < 4; i++) { v[i] = lds2(sbase + O_P2 + off + i * 5120); v2[i] = lds2(sbase + O_P2 + off + o2 + i * 5120); }
    auto bad2 = [&]() {
      return any(or3(or3(diff2(v[0].x, v[1].x, tagv), diff2(v[2].x, v[3].x, tagv), diff2(v2[0].x, v2[1].x, tagv)), diff2(v2[2].x, v2[3].x, tagv), 0) & 1);
    };
    if (__builtin_expect(bad2() && nl, 0)) {
      FAILCNT(0);
      int it = 0;
      do {
#pragma unroll
        for (int i = 0; i < 4; i++) {
          v[i] = ld_rlx2(reinterpret_cast<const uint8_t*>(zin) + off + i * 5120);
          v2[i] = ld_rlx2(reinterpret_cast<const uint8_t*>(zin) + off + o2 + i * 5120);
        }
      } while (bad2() && ++it < SPIN_MAX);
    }
#pragma unroll 1
    for (int ln = 0; ln < nl; ln++, offo += do2, po = 2048) {
      float d[4][4];
      uint32_t A[8];
#pragma unroll
      for (int h = 0; h < 2; h++) {
        mma16<false>(d[2 * h], cf[0][0].x, cf[0][0].y, cf[0][0].z, cf[0][0].w, v[h].x, v[2 + h].x);
        mma16<false>(d[2 * h + 1], cf[1][0].x, cf[1][0].y, cf[1][0].z, cf[1][0].w, v[h].y, v[2 + h].y);
      }
      if (ln) { fence_async_smem(); bar_arrive(15, NTHR); }
#pragma unroll
      for (int h = 0; h < 2; h++)
#pragma unroll
        for (int L = 0; L < 2; L++) {
          const uint4 tw = cf[L][2 + h];
          const float* z = d[2 * h + L];
          const float2 z0 = cmul(make_float2(z[0], z[2]), make_float2(__uint_as_float(tw.x), __uint_as_float(tw.y)));
          const float2 z1 = cmul(make_float2(z[1], z[3]), make_float2(__uint_as_float(tw.z), __uint_as_float(tw.w)));
          A[4 * h + L] = pack_bf16(z0.x, z0.y); A[4 * h + 2 + L] = pack_bf16(z1.x, z1.y);
        }
#pragma unroll
      for (int tt = 0; tt < 4; tt++) {
        mma16<false>(d[tt], A[0], A[1], A[2], A[3], G[tt].x, G[tt].y);
        mma16<true>(d[tt], A[4], A[5], A[6], A[7], G[tt].z, G[tt].w);
      }
#pragma unroll
      for (int tt = 0; tt < 4; tt++) {
        const float ar = d[tt][0], aj = d[tt][1], br = d[tt][2], bj = d[tt][3];
        const float2 y1 = cmul(make_float2(fmaf(-al, bj, ar), fmaf(al, br, aj)), make_float2(wc[4 * tt], wc[4 * tt + 1]));
        const float2 y2 = cmul(make_float2(fmaf(al, ar, bj), fmaf(al, aj, -br)), make_float2(wc[4 * tt + 2], wc[4 * tt + 3]));
        A[2 * tt] = pack_bf16(fmaf(al, y2.x, y1.x), fmaf(-al, y2.y, -y1.y));
        A[2 * tt + 1] = pack_bf16(fmaf(al, y1.y, -y2.y), fmaf(al, y1.x, -y2.x));
      }
#pragma unroll
      for (int i = 0; i < 16; i++) wc[i] = wn[i];
#pragma unroll
      for (int i = 0; i < 4; i++) v[i] = v2[i];
#pragma unroll
      for (int tt = 0; tt < 4; tt++) {
        mma16<false>(d[tt], A[0], A[1], A[2], A[3], G[tt].x, G[tt].y);
        mma16<true>(d[tt], A[4], A[5], A[6], A[7], G[tt].z, G[tt].w);
      }
#pragma unroll
      for (int h = 0; h < 2; h++)
#pragma unroll
        for (int L = 0; L < 2; L++) {
          const uint4 tw = cf[L][2 + h];
          const float2 z0 = cmul(make_float2(d[2 * h][2 * L], d[2 * h][2 * L + 1]), make_float2(__uint_as_float(tw.x), __uint_as_float(tw.y)));
          const float2 z1 = cmul(make_float2(d[2 * h + 1][2 * L], d[2 * h + 1][2 * L + 1]), make_float2(__uint_as_float(tw.z), __uint_as_float(tw.w)));
          A[4 * h + 2 * L] = movm(pack_bf16(z0.x, z1.x)); A[4 * h + 2 * L + 1] = movm(pack_bf16(z0.y, z1.y));
        }
#pragma unroll
      for (int h = 0; h < 2; h++) {
        mma16<false>(d[0], cf[0][1].x, cf[0][1].y, cf[0][1].z, cf[0][1].w, A[4 * h], A[4 * h + 1]);
        mma16<false>(d[1], cf[1][1].x, cf[1][1].y, cf[1][1].z, cf[1][1].w, A[4 * h + 2], A[4 * h + 3]);
#pragma unroll
        for (int e = 0; e < 2; e++)
          sts2(offo + (2 * h + e) * po, set_tag(pack_bf16(d[0][e], d[0][2 + e]), tagv), pack_bf16(d[1][e], d[1][2 + e]));
      }
      CK(12 + ln);
    }
    fence_async_smem();
    if (nl < 2 && wp != 8) bar_arrive(15, NTHR);
    if (wp & 7) { if (wg < 2) bar_arrive(6, 256); }
    else {
      if (wp) bar_sync(15, NTHR); else bar_sync(6, 256);
      if (elect()) {
        tma_st2d(mz2, sz2, cz2, 0);
        HW();
        if (wp == 0) { red_add(hz2, 1); TS(9); }
      }
      __syncwarp();
    }
  }
  if (wg == 2) {
#pragma unroll 1
    for (int u = 72 + cta, k = 0; u < 216; u += NCTA, k ^= 1) {
      if (R < 0) { fence_async_smem(); bar_sync(4, 128); load_wm(u); }
      mod_unit(sc, u, t128, sbase + O_NRM, full0 + 8 * B_WM, k, red + 256 - 256 * k, tag16);
    }
    fence_async_smem();
    CK(13);
  }

  const int grp = cta / 11, m1 = cta - 11 * grp;
  const bool helper = (m1 & 3) == 3;
  const int f1 = 384 * grp + (helper ? 192 : 128) * (m1 >> 2);
  const int d1 = 160 * (m1 & 3), flip = m1 >= 7;
  const int a1bytes = helper ? 24576 : 16384;
  auto load_a1 = [&](int st, int kb) {
    mbar_expect(full0 + 8 * st, a1bytes);
    tma4d_ef(sbase + st * STAGE, helper ? &maps.w1b : &maps.w1a, 4 * (kb >> 3), 16 * (kb & 7), f1 >> 6, full0 + 8 * st);
  };

  if (rows) {
#pragma unroll
    for (int kk = 0; kk < 4; kk++) af[kk] = __ldg(p.tab + TB_E + kk * 128 + t128);
    const uint4 c0 = lds4(sbase + O_ST + tid * 16), c1 = lds4(sbase + O_ST + 6144 + tid * 16);
    const uint2 c2 = lds2(sbase + O_ST + 12288 + tid * 8);
    const uint32_t tb[4] = {c0.x, c0.y, c0.z, c0.w}, sy[6] = {c1.x, c1.y, c1.z, c1.w, c2.x, c2.y};
    const uint32_t l8 = pin(8 * l), syl = pin(sbase + O_Y + wp * 2336 + 8 * l);
    uint32_t sh3[3], ham[3];
#pragma unroll
    for (int k = 0; k < 3; k++) {
      const int pos = k && (l >> 4) == k - 1 ? (l & 8) + 4 * (l & 1) + ((l >> 1) & 3) : 4 * (l & 3) + ((l >> 2) & 3);
      const int sw = 2 * cta + (wp & 1), ph = pos ^ ((sw & 3) << 2);
      sh3[k] = pin(sbase + O_B3 + (wp >> 1) * 4608 + (l >> 4) * 256 + (wp & 1) * 128 + ph * 4);
      const bool tg = ((ph ^ sw) & 7) == 0;
      ham[k] = pin(tg ? ~1u : ~0u);
    }
    const int slot = 4 * (cta >> 4) + ((cta >> 1) & 3) + 32 * (2 * ((cta >> 3) & 1) + (cta & 1));
    const uint32_t* zin = sc->z2 + (size_t)slot * 4800;
    uint32_t ga[9];
    uint2 sh[9], sw[9];
    auto load_mod3 = [&](int part) {
#pragma unroll
      for (int i = 0; i < 9; i++) {
        if (part != 2) { const uint2 v = lds2(l8 + sbase + O_MOD + 256 * i); ga[i] = __byte_perm(v.x, v.y, 0x7632); }
        if (part != 1) { sh[i] = lds2(l8 + sbase + O_MOD + 4 * D_ + 256 * i); sw[i] = lds2(l8 + sbase + O_MOD + 8 * D_ + 256 * i); }
      }
    };
    if (wg == 2) {
      {
        uint4 v[4];
        const int i3 = min(t128 + 384, 431);
        int it = 0;
        while (true) {
          uint32_t bad = 0;
#pragma unroll
          for (int k = 0; k < 4; k++) v[k] = ld_rlx4(sc->mod + 4 * (k < 3 ? t128 + 128 * k : i3));
#pragma unroll
          for (int k = 0; k < 4; k++) {
            v[k].x ^= tag16; v[k].y ^= tag16; v[k].z ^= tag16; v[k].w ^= tag16;
            bad |= v[k].x | v[k].y | v[k].z | v[k].w;
          }
          if (!any(bad & 0xffffu) || ++it > SPIN_MAX) break;
        }
#pragma unroll
        for (int k = 0; k < 4; k++) sts4(sbase + O_MOD + 16 * (k < 3 ? t128 + 128 * k : i3), v[k].x, v[k].y, v[k].z, v[k].w);
      }
      CK(14);
      bar_sync(10, NTHR);
      mbar_wait(full0 + 8 * B_Z2, 0);
      if (elect()) {
        load_a1(wp - 8, wp - 8);
        if (wp > 8 && wp - 8 < NG1) prefetch_l2(reinterpret_cast<const uint8_t*>(p.w1) + (size_t)(128 * (4 * ((wp - 8) >> 1) + (cta >> 5)) + 64 * (wp & 1) + 2 * (cta & 31)) * (2 * F_), 4 * F_);
      }
      __syncwarp();
    } else {
      const uint4 e0 = lds4(sbase + O_ST + 15360 + tid * 16), e1 = lds4(sbase + O_ST + 19456 + tid * 16), e2 = lds4(sbase + O_ST + 23552 + tid * 16);
      const uint32_t lo[9] = {e0.x, e0.y, e0.z, e0.w, e1.x, e1.y, e1.z, e1.w, e2.x}, lx = e2.y, sb3 = e2.z;
      if (MODPOS == 0) bar_arrive(10, NTHR);
      CK(14);
      if (wp == 1) {
        const uint32_t* zu = upin(zin);
        if (elect()) mbar_expect(full0 + 8 * B_Z2, 19200);
        wait_cnt(&sc->cnt[C_Z2], 120 * ep);
        if (elect()) {
          bulk_ld(sbase + O_IN, zu, 19200, full0 + 8 * B_Z2);
          TS(14);
        }
        __syncwarp();
      }
      if (MODPOS) { bar_sync(10, NTHR); load_mod3(MODPOS - 1); }
      mbar_wait(full0 + 8 * B_Z2, 0);
      CK(15);
      if (tid == 0) TS(11);
      uint2 v[10];
#pragma unroll
      for (int k1 = 0; k1 < 10; k1++) v[k1] = lds2(k1 < 9 ? lo[k1] : lx);
      auto bad3 = [&]() {
        return any(or3(or3(diff2(v[0].x, v[1].x, tag1), diff2(v[2].x, v[3].x, tag1), diff2(v[4].x, v[5].x, tag1)), diff2(v[6].x, v[7].x, tag1), diff2(v[8].x, v[9].x, tag1)) & 1);
      };
      if (__builtin_expect(bad3(), 0)) {
        FAILCNT(1);
        int it = 0;
        do {
#pragma unroll
          for (int k1 = 0; k1 < 10; k1++) v[k1] = ld_rlx2(reinterpret_cast<const uint8_t*>(zin) + ((k1 < 9 ? lo[k1] : lx) - (sbase + O_IN)));
        } while (bad3() && ++it < SPIN_MAX);
      }
      float2 za[9], zb[9];
#pragma unroll
      for (int i = 0; i < 9; i++) { za[i] = make_float2(bf_lo(v[i].x), bf_hi(v[i].x)); zb[i] = make_float2(bf_lo(v[i].y), bf_hi(v[i].y)); }
      if (kap == 0) {
#pragma unroll
        for (int k = 1; k < 5; k++) {
          float2 a = za[k], b = za[9 - k];
          za[k] = make_float2(a.x - b.y, a.y + b.x); za[9 - k] = make_float2(a.x + b.y, b.x - a.y);
          a = zb[k]; b = zb[9 - k];
          zb[k] = make_float2(a.x - b.y, a.y + b.x); zb[9 - k] = make_float2(a.x + b.y, b.x - a.y);
        }
        za[0].y = bf_lo(v[9].x); zb[0].y = bf_lo(v[9].y);
      }
      __syncwarp();
      dft9(za); dft9(zb);
#pragma unroll
      for (int n = 0; n < 8; n += 2) {
        const int i0 = (9 - n) % 9, i1 = 8 - n;
        stmatrix4(sb3 + n * 2048, pack_bf16(za[i0].x, zb[i0].x), pack_bf16(za[i0].y, zb[i0].y), pack_bf16(za[i1].x, zb[i1].x), pack_bf16(za[i1].y, zb[i1].y));
      }
      stmatrix2(sb3 + 8 * 2048, pack_bf16(za[1].x, zb[1].x), pack_bf16(za[1].y, zb[1].y));
      fence_async_smem();
    }
    CK(16);
    __syncthreads();
    CK(17);
    float acc[24];
    const uint32_t db = (((sbase + O_B3 + wg * 6144) & 0x3FFFF) >> 4) | ((128 >> 4) << 16);
    wg_fence();
#pragma unroll
    for (int kk = 0; kk < 4; kk++) wgmma_rs_48(acc, af[kk].x, af[kk].y, af[kk].z, af[kk].w, db + kk * 16, 1024 >> 4, kk);
    wg_commit();
    if (wg < 2 && MODPOS == 0) load_mod3(0);
    wg_wait<0>();
    reg_fence(acc);
    CK(18);
#pragma unroll
    for (int i = 0; i < 3; i++) {
      const float* a = &acc[8 * i];
      const uint32_t a0 = pack_bf16(a[0], a[1]), a1 = pack_bf16(a[2], a[3]), a2 = pack_bf16(a[4], a[5]), a3 = pack_bf16(a[6], a[7]);
#pragma unroll
      for (int jh = 0; jh < 2; jh++) {
        float y[4];
        mma16<false>(y, a0, a1, a2, a3, tb[2 * jh], tb[2 * jh + 1]);
        sts(sy[2 * i] + jh * (4 * 584 * 4), pack_bf16(y[0], y[1]));
        sts(sy[2 * i + 1] + jh * (4 * 584 * 4), pack_bf16(y[2], y[3]));
      }
    }
    CK(19);
    if (wg == 2) { bar_arrive(7, NTHR); if (W2H) bar_sync(15, NTHR); }
    else {
      bar_sync(7, NTHR);
      CK(20);
      float a[18], b[18];
#pragma unroll
      for (int i = 0; i < 9; i++) {
        const uint2 y = lds2(syl + 256 * i);
        xr[i] = hfma2(ga[i], __byte_perm(y.x, y.y, 0x5410), xr[i]);
        xr[9 + i] = hfma2(ga[i], __byte_perm(y.x, y.y, 0x7632), xr[9 + i]);
        a[2 * i] = bf_lo(xr[i]); a[2 * i + 1] = bf_hi(xr[i]); b[2 * i] = bf_lo(xr[9 + i]); b[2 * i + 1] = bf_hi(xr[9 + i]);
      }
      float oa, ra, ob, rb;
      if (MODPOS == 2) load_mod3(2);
      ln_stats2(a, b, 1.0f, oa, ra, ob, rb);
      CK(21);
      if (W2H == 1) bar_arrive(15, NTHR);
#pragma unroll
      for (int i = 0; i < 9; i++) {
        const float c0 = __uint_as_float(sw[i].x), c1 = __uint_as_float(sw[i].y), s0 = __uint_as_float(sh[i].x), s1 = __uint_as_float(sh[i].y);
        a[2 * i] = fmaf(fmaf(a[2 * i], ra, oa), c0, s0); a[2 * i + 1] = fmaf(fmaf(a[2 * i + 1], ra, oa), c1, s1);
        b[2 * i] = fmaf(fmaf(b[2 * i], rb, ob), c0, s0); b[2 * i + 1] = fmaf(fmaf(b[2 * i + 1], rb, ob), c1, s1);
      }
      ln_stats2(a, b, 0.5f, oa, ra, ob, rb);
      CK(22);
      if (W2H == 2) bar_arrive(15, NTHR);
#pragma unroll
      for (int i = 0; i < 9; i++) {
        const int k = i == 2 ? 1 : i == 6 ? 2 : 0;
        sts(sh3[k] + i * 512, bitsel(pack_bf16(fmaf(a[2 * i], ra, oa), fmaf(a[2 * i + 1], ra, oa)), ham[k], tag1));
        sts(sh3[k] + i * 512 + 64, bitsel(pack_bf16(fmaf(b[2 * i], rb, ob), fmaf(b[2 * i + 1], rb, ob)), ham[k], tag1));
      }
      fence_async_smem();
      if (wp < 2 * H3G) bar_arrive(8, 32 + 64 * H3G); else bar_arrive(9, 288 - 64 * H3G);
      CK(23);
    }
  } else __syncthreads();

  const bool g2 = cta < 130 && (cta >> 1) != 56;
  const int z2 = cta < 112 ? cta : cta - 2, r = z2 >> 6;
  const int s2 = 128 * ((z2 >> 2) & 15), d2 = 144 * (z2 & 3);
  constexpr int ST0 = (32 - JSK - 1) % NST, ST1 = 31 % NST;

  if (wg == 2) {
    asm volatile("setmaxnreg.dec.sync.aligned.u32 40;");
    auto load_b = [&](bool second, int i, int st) {
      const uint32_t lb = full0 + 8 * (B_LAND + st), bytes = second ? 18432 : STAGE - a1bytes;
      mbar_expect(lb, bytes);
      bulk_ld(sbase + (second ? st * STAGE2 + 16384 : st * STAGE + a1bytes),
              second ? sc->u + ((size_t)(36 * r + kb2_order(i)) * D_ + d2) * 128 : sc->h3 + ((size_t)(i * 18 + (d1 >> 5)) << 12), bytes, lb);
    };
    if (wp == 8) {
      int st = rows ? 4 : 0, ph = 1;
#pragma unroll 1
      for (int kb = st; kb < 32; kb++) {
        if (rows && (kb >> 1) == 2) mbar_wait(full0 + 8 * (B_S4 - 4 + kb), 0);
        mbar_wait(empty0 + 8 * st, ph);
        if (elect()) {
          load_a1(st, kb);
          if (kb >= PF2K && kb < PF2K + PF2 && g2)
            prefetch_l2(reinterpret_cast<const uint8_t*>(p.w2) + (size_t)(36 * r + kb2_order(kb - PF2K)) * 262144 + (z2 & 63) * 4096, 4096);
        }
        __syncwarp();
        ring_next<false>(st, ph);
      }
      if (g2) {
        st++;
#pragma unroll 1
        for (int i = 0; i < 36; i++) {
          if (i == HOLDA) mbar_wait(full0 + 8 * B_GO, 0);
          mbar_wait(empty0 + 8 * st, ph);
          if (elect()) {
            mbar_expect(full0 + 8 * st, 16384);
            tma3d_ef(sbase + st * STAGE2, &maps.w2, 64 * (36 * r + kb2_order(i)), s2 >> 6, full0 + 8 * st);
          }
          __syncwarp();
          ring_next<true>(st, ph);
        }
      }
    } else if (wp >= 10) {
      const int sw = wp - 10;
      if (rows) {
        const CUtensorMap* mp = upin(&maps.h3[sw]);
        const uint32_t src = upin(sbase + O_B3 + sw * (H3G * 4608)), c0 = upin(64 * (cta & 15)), c1 = upin(18 * (cta >> 4)), c2 = upin(H3G * sw);
        unsigned* flag = pin(&sc->cnt[C_H3 + (cta >> 4) + 8 * sw]);
        bar_sync(8 + sw, sw ? 288 - 64 * H3G : 32 + 64 * H3G);
        if (sw) mbar_wait(full0 + 8 * H3W, 0);
        if (elect()) {
          tma_st3d(mp, src, c0, c1, c2);
          mbar_arrive(full0 + 8 * B_S4);
          bulk_commit_wait();
          red_add(flag, 1);
          mbar_arrive(full0 + 8 * B_S5);
          TS(sw ? 24 : 13);
        }
        __syncwarp();
      }
      if (sw) {
        if (rows) {
          mbar_wait(full0 + 8 * B_S5, 0);
          if (elect()) { asm volatile("fence.acq_rel.gpu;" ::: "memory"); red_add(&sc->cnt[C_X + 64], 1); }
          __syncwarp();
        }
        if (g2) {
          uint2 v[3];
          int it = 0;
          do {
#pragma unroll
            for (int i = 0; i < 3; i++) v[i] = ld_rlx2(sc->mod + 3 * D_ + d2 + 2 * min(l + 32 * i, 71));
          } while (any(or3(diff2(v[0].x, v[0].y, tag16), diff2(v[1].x, v[1].y, tag16), diff2(v[2].x, v[2].y, tag16)) & 0xffffu) && ++it < SPIN_MAX);
#pragma unroll
          for (int i = 0; i < 3; i++) sts(sbase + O_GB + 4 * min(l + 32 * i, 71), __byte_perm(v[i].x, v[i].y, 0x7632));
          __syncwarp();
        }
        wait_cnt<true>(&sc->cnt[C_X + 64], 128 * ep);
        if (elect()) mbar_arrive(full0 + 8 * B_X);
        __syncwarp();
      }
      uint32_t lph = 0;
      auto check_tiles = [&](bool second, int n, int st, uint32_t o1, uint32_t d2nd) {
        const uint32_t b1 = pin(sbase + o1), b2 = pin(sbase + o1 + d2nd);
        int i = 0, it = 0;
#pragma unroll 1
        do {
          const uint32_t so = st * (second ? STAGE2 : STAGE);
          mbar_wait(full0 + 8 * (B_LAND + st), (lph >> st) & 1);
          lph ^= 1u << st;
          uint32_t v[20];
#pragma unroll
          for (int k = 0; k < 20; k++) if (!second || k < 10 || k >= 12) v[k] = lds(k < 12 ? b1 + so + k * 1024 : b2 + so + (k - 12) * 1024); else v[k] = tag1;
#pragma unroll
          for (int k = 0; k < 10; k++) v[k] = diff2(v[2 * k], v[2 * k + 1], tag1);
          const uint32_t bad = or3(or3(or3(v[0], v[1], v[2]), or3(v[3], v[4], v[5]), v[6]), v[7], or3(v[8], v[9], 0));
          if (__builtin_expect(any(bad & 1) && ++it < SPIN_MAX, 0)) {
            FAILCNT(2 + second);
            fence_async_smem();
            __syncwarp();
            if (elect()) load_b(second, i, st);
            __syncwarp();
            continue;
          }
          if (elect()) mbar_arrive(full0 + 8 * st);
          if (++st == NST) st = 0;
          i++;
        } while (i < n);
      };
      if (!sw) check_tiles(false, NV1, 0, a1bytes + l * 32 + (l >> 2) * 4, helper ? 4096 : 12288);
      const bool first = helper || m1 < W0N;
#pragma unroll 1
      for (int k = sw ? first : !first; k <= sw; k++) {
        const uint32_t stg = sbase + (!k ? ST0 * STAGE : helper ? ST1 * STAGE : O_U1);
        const int kbA = (f1 >> 6) + (helper ? 2 : 1) * (k ^ flip), kbB = helper ? (f1 >> 6) + 1 : kbA;
        uint8_t* const uA = upin(sc->u + ((size_t)kbA * D_ + d1) * 128);
        uint8_t* const uB = upin(sc->u + ((size_t)kbB * D_ + (helper ? d1 : d1 + 96)) * 128);
        unsigned* const fA = pin(&sc->cnt[C_U + kbA]);
        unsigned* const fB = pin(&sc->cnt[C_U + kbB]);
        const bool slow = sw && !helper;
        bar_sync(11 + k, 160);
        if (!slow) { if (elect()) { bulk_st(uA, stg, 96 * 128); TS(k ? 31 : 30); } __syncwarp(); }
        bar_sync(13 + k, 160);
        if (slow) {
          if (g2) mbar_wait(full0 + 8 * B_GO, 0);
          if (first) pause(10 * TRK0);
#pragma unroll 1
          for (int i = 0; i < 20480; i += 2048) {
            if (elect()) bulk_st(uA + i, stg + i, 2048);
            pause(k ? TRKC : TRK0);
          }
        }
        if (elect()) {
          if (helper ? k : !slow) bulk_st(uB, stg + 96 * 128, helper ? 96 * 128 : 64 * 128);
          bulk_commit_wait();
          red_add(fA, 1);
          if (helper && k) red_add(fB, 1);
          if (!k || helper) mbar_arrive(empty0 + 8 * (k ? ST1 : ST0));
          TS(k ? 23 : 17);
          mbar_arrive(full0 + 8 * B_S5);
        }
        __syncwarp();
      }
      if (sw) {
        mbar_wait(full0 + 8 * B_S5, rows);
        if (elect()) { asm volatile("fence.acq_rel.gpu;" ::: "memory"); red_add(&sc->cnt[C_X], 1); }
        __syncwarp();
      }
      if (g2) {
        if (!sw) check_tiles(true, NV2, 3, 16384 + l * 32 + (4 * (g & 1) + (g >> 1)) * 4, 10240);
        else {
          wait_cnt<true>(&sc->cnt[C_X], NCTA * ep);
          if (elect()) {
            mbar_arrive(full0 + 8 * B_X);
            if (cta == 0) sc->cnt[C_EP] = ep;
          }
          __syncwarp();
        }
      }
      __syncwarp();
    } else {
      uint64_t ready = 0;
      int st = 0, ph = 1;
#pragma unroll 1
      for (int kb = 0; kb < 32; kb++) {
        const uint8_t* src = upin(sc->h3 + ((size_t)(kb * 18 + (d1 >> 5)) << 12));
        const uint32_t dst = upin(sbase + st * STAGE + a1bytes), lb = full0 + 8 * ((kb < NV1 ? B_LAND : 0) + st);
        if (kb == NV1) { mbar_wait(full0 + 8 * B_X, 0); fence_async_glb(); ready = ~0ull; }
        if (rows && (kb >> 1) == 2) mbar_wait(full0 + 8 * (B_S4 - 4 + kb), 0);
        mbar_wait(empty0 + 8 * st, ph);
        if (elect()) mbar_expect(lb, STAGE - a1bytes);
        wait_flags(sc->cnt + C_H3, 32, (kb & 7) + (kb < 8 * H3G ? 0 : 8), 16 * ep, ready);
        if (elect()) bulk_ld(dst, src, STAGE - a1bytes, lb);
        ring_next<false>(st, ph);
      }
      if (g2) {
        ready = 0;
        st++;
#pragma unroll 1
        for (int i = 0; i < 36; i++) {
          const int kb = kb2_order(i);
          const uint8_t* src = upin(sc->u + ((size_t)(36 * r + kb) * D_ + d2) * 128);
          const uint32_t dst = upin(sbase + st * STAGE2 + 16384), lb = full0 + 8 * ((i < NV2 ? B_LAND : 0) + st);
          if (i == NV2) { mbar_wait(full0 + 8 * B_X, 1); fence_async_glb(); ready = ~0ull; }
          mbar_wait(empty0 + 8 * st, ph);
          if (elect()) mbar_expect(lb, 18432);
          wait_flags(sc->cnt + C_U + 36 * r, 36, kb, 4 * ep, ready);
          if (elect()) {
            bulk_ld(dst, src, 18432, lb);
            if (i == GOAT) mbar_arrive(full0 + 8 * B_GO);
          }
          ring_next<true>(st, ph);
        }
      }
    }
  } else {
    asm volatile("setmaxnreg.inc.sync.aligned.u32 232;");
    const int wgu = wg;
    constexpr uint32_t sb4 = sbase >> 4;
    const int w = wp & 3;
    Ring rg = {0, 0};
    uint32_t* const x1p = p.out + (size_t)(cta + 256 * wp) * 288 + l;
    const uint32_t ad = pin(sbase + (!wg ? ST0 * STAGE : helper ? ST1 * STAGE : O_U1) + (8 * (l >> 4) + (l & 7)) * 128 + (((2 * w + ((l >> 3) & 1)) ^ (l & 7)) << 4));
    const uint32_t uam = pin(g == 2 * t ? 0xfffefffeu : ~0u), uom = tag1 * 0x10001u;
    float acc[96];
    constexpr uint32_t LA = (8192 >> 4) << 16, LB = (4096 >> 4) << 16;
    {
      const int fa = f1 + (helper ? 128 : 64) * (wg ^ flip) + 16 * w + g, fb = helper ? f1 + 64 + 16 * w + g : fa;
      const float a0 = 0.5f * __bfloat162float(p.b1[fa]), a1 = 0.5f * __bfloat162float(p.b1[fa + 8]);
      const float b0 = 0.5f * __bfloat162float(p.b1[fb]), b1 = 0.5f * __bfloat162float(p.b1[fb + 8]);
#pragma unroll
      for (int i = 0; i < 96; i++) acc[i] = i < 48 ? ((i & 2) ? a1 : a0) : ((i & 2) ? b1 : b0);
      reg_fence(acc);
    }
    if (!helper) gemm_main<0>(acc, sb4 + (wgu ^ flip) * 512 + LA, 0, sb4 + 1024 + LB, wgu, rg, x1p, xr);
    else {
      float ac2[96];
#pragma unroll
      for (int i = 0; i < 96; i++) asm volatile("mov.b32 %0, %1;" : "=f"(ac2[i]) : "f"(acc[i]));
      gemm_main<1>(ac2, sb4 + (wgu ^ flip) * 1024 + LA, sb4 + 512 + LA, sb4 + 1536 + LB, wgu, rg, x1p, xr);
#pragma unroll
      for (int i = 0; i < 96; i++) asm volatile("mov.b32 %0, %1;" : "=f"(acc[i]) : "f"(ac2[i]));
    }
    if (t128 == 0) { TS(wg ? 16 : 6); if (wg) TSC(5); }
    {
      float tp[2] = {0.f, 0.f};
#pragma unroll
      for (int j = 0; j < 12; j++) {
        const float* a = &acc[8 * j];
        const float k3 = j < 2 ? GK3 : fmaf(tp[j & 1], 0.0f, GK3);
        float o[8];
#pragma unroll
        for (int e = 0; e < 8; e++) {
          float z = a[e] * fmaf(a[e] * k3, a[e], GK1);
          asm("tanh.approx.f32 %0, %0;" : "+f"(z));
          if (e == GDEP) tp[j & 1] = z;
          o[e] = fmaf(a[e], z, a[e]);
        }
        stmatrix4t(ad + j * 2048, bitsel(pack_bf16(o[0], o[1]), uam, uom), pack_bf16(o[2], o[3]), bitsel(pack_bf16(o[4], o[5]), uam, uom), pack_bf16(o[6], o[7]));
        if (j == 5) {
          fence_async_smem();
          bar_arrive(11 + wgu, 160);
        }
        if ((j == 5 && helper && !wgu) || (j == 9 && !helper)) break;
      }
      fence_async_smem();
      bar_arrive(13 + wgu, 160);
      if (t128 == 0) TS(wg ? 29 : 28);
    }
    if (g2) {
      const int mb = wgu ^ r;
      const int odd = z2 & 1;
      uint4 gq[4];
      uint2 gs;
      {
        float a0 = 0.f, a1 = 0.f;
        if (wgu) { a0 = __bfloat162float(p.b2[s2 + 64 * mb + 16 * w + g]); a1 = __bfloat162float(p.b2[s2 + 64 * mb + 16 * w + 8 + g]); }
#pragma unroll
        for (int i = 0; i < 4; i++) gq[i] = lds4(sbase + O_GB + 32 * odd + 64 * i + 16 * t);
        gs = lds2(sbase + O_GB + (odd ? 0 : 256) + 8 * t);
#pragma unroll
        for (int i = 0; i < 72; i++) acc[i] = (i & 2) ? a1 : a0;
      }
      uint32_t* const ob = p.out + (size_t)(s2 + 64 * mb + 16 * w + g) * 288 + (d2 >> 1);
      uint32_t* const oq = pin(ob + 8 * odd + 4 * t);
      uint32_t* const os = pin(ob + (odd ? 0 : 64) + 2 * t);
      rg.st++;
      gemm_main<3>(acc, sb4 + mb * 512 + LA, 0, sb4 + 1024 + (1 << 16), wgu, rg, x1p, xr);
      if (t128 == 0) { TS(wg ? 20 : 19); if (wg) TSC(22); }
      auto finish = [&](const float* aq, const float* as) {
#pragma unroll
        for (int i = 0; i < 8; i++) {
          const float* a = aq + 16 * (i >> 1) + 2 * (i & 1);
          const uint4 gv = gq[i >> 1];
          red_bf16x8(oq + (i & 1) * 2304 + 16 * (i >> 1), hmul2(gv.x, pack_bf16(a[0], a[1])), hmul2(gv.y, pack_bf16(a[4], a[5])),
                     hmul2(gv.z, pack_bf16(a[8], a[9])), hmul2(gv.w, pack_bf16(a[12], a[13])));
        }
#pragma unroll
        for (int i = 0; i < 2; i++) red_bf16x4(os + i * 2304, hmul2(gs.x, pack_bf16(as[2 * i], as[2 * i + 1])), hmul2(gs.y, pack_bf16(as[2 * i + 4], as[2 * i + 5])));
      };
      if (odd) finish(&acc[8], &acc[0]); else finish(&acc[0], &acc[64]);
      if (t128 == 0) TS(wg ? 7 : 21);
      __syncwarp();
    }
  }
}

typedef CUresult (*EncodeFn)(CUtensorMap*, CUtensorMapDataType, cuuint32_t, void*, const cuuint64_t*, const cuuint64_t*, const cuuint32_t*,
                             const cuuint32_t*, CUtensorMapInterleave, CUtensorMapSwizzle, CUtensorMapL2promotion, CUtensorMapFloatOOBfill);

struct Dim { cuuint64_t n, stride; cuuint32_t box; };
template <int RANK>
void make_map(EncodeFn enc, CUtensorMap* m, bool words, int swz, const void* ptr, const Dim (&d)[RANK]) {
  cuuint64_t gd[RANK], gs[RANK];
  cuuint32_t bx[RANK], es[RANK];
  for (int i = 0; i < RANK; i++) { gd[i] = d[i].n; gs[i] = d[i].stride; bx[i] = d[i].box; es[i] = 1; }
  enc(m, words ? CU_TENSOR_MAP_DATA_TYPE_UINT32 : CU_TENSOR_MAP_DATA_TYPE_BFLOAT16, RANK, const_cast<void*>(ptr), gd, gs + 1, bx, es,
      CU_TENSOR_MAP_INTERLEAVE_NONE, static_cast<CUtensorMapSwizzle>(swz),
      swz == 3 ? CU_TENSOR_MAP_L2_PROMOTION_L2_256B : CU_TENSOR_MAP_L2_PROMOTION_NONE, CU_TENSOR_MAP_FLOAT_OOB_FILL_NONE);
}

}

extern "C" void kernel_launch(void* const* d_in, const int* in_sizes, int n_in, void* d_out, int out_size) {
  (void)in_sizes; (void)n_in; (void)out_size;
  static EncodeFn enc = nullptr;
  static void *sptr = nullptr, *tptr = nullptr;
  if (!enc) {
    void* f = nullptr; cudaDriverEntryPointQueryResult qr;
    cudaGetDriverEntryPoint("cuTensorMapEncodeTiled", &f, cudaEnableDefault, &qr);
    enc = reinterpret_cast<EncodeFn>(f);
    cudaFuncSetAttribute(fused_kernel, cudaFuncAttributeMaxDynamicSharedMemorySize, SMEM_BYTES);
    cudaGetSymbolAddress(&sptr, g_s);
    cudaGetSymbolAddress(&tptr, T_TAB);
  }
  Params p;
  p.x = (const __nv_bfloat16*)d_in[0]; p.wr = (const __nv_bfloat16*)d_in[1]; p.wi = (const __nv_bfloat16*)d_in[2];
  p.b1 = (const __nv_bfloat16*)d_in[5]; p.b2 = (const __nv_bfloat16*)d_in[7];
  p.c = (const __nv_bfloat16*)d_in[8]; p.wmod = (const __nv_bfloat16*)d_in[9];
  p.w1 = (const __nv_bfloat16*)d_in[4]; p.w2 = (const __nv_bfloat16*)d_in[6];
  p.out = static_cast<uint32_t*>(d_out); p.s = static_cast<Scratch*>(sptr); p.tab = static_cast<const uint4*>(tptr);
  Maps maps;
  make_map<4>(enc, &maps.w1a, false, 3, p.w1, {{64, 0, 64}, {16, 128 * 2 * F_, 4}, {128, 2 * F_, 16}, {72, 128, 2}});
  make_map<4>(enc, &maps.w1b, false, 3, p.w1, {{64, 0, 64}, {16, 128 * 2 * F_, 4}, {128, 2 * F_, 16}, {72, 128, 3}});
  make_map<3>(enc, &maps.w2, false, 3, p.w2, {{64, 0, 64}, {F_, 2 * S_, 64}, {32, 128, 2}});
  make_map<2>(enc, &maps.z1, true, 0, p.s->z1, {{5120, 0, 40}, {120, 20480, 60}});
  for (int i = 0; i < 2; i++) make_map<2>(enc, &maps.z2[i], true, 0, p.s->z2, {{4800, 0, i ? 16u : 24u}, {128, 19200, 128}});
  for (int i = 0; i < 4; i++) make_map<2>(enc, &maps.wf[i], false, 2 - (i & 1), (i & 2) ? p.wi : p.wr, {{16 * DF_, 0, (i & 1) ? 16u : 32u}, {128, 32 * DF_, 128}});
  make_map<2>(enc, &maps.wm, false, 1, p.wmod, {{6 * D_, 0, 16}, {D_, 12 * D_, 192}});
  for (int i = 0; i < 2; i++) make_map<3>(enc, &maps.h3[i], true, 0, p.s->h3, {{1024, 0, 64}, {144, 4096, 18}, {4, 144 * 4096, i ? 4u - H3G : H3G}});
  fused_kernel<<<NCTA, NTHR, SMEM_BYTES, cudaStreamPerThread>>>(p, maps);
}
```

```cpp
#include <cuda_runtime.h>
#include <cuda_bf16.h>
#include <cuda.h>
#include <stdint.h>

namespace {

constexpr int S_ = 2048, D_ = 576, DF_ = 289, F_ = 4608;
constexpr int NCTA = 132, NTHR = 384;
constexpr int STAGE = 36864, NST = 6;
constexpr int STAGE2 = 34816, O_U1 = NST * STAGE2, O_GB = O_U1 + 20480, SMEM_BYTES = 232448;
constexpr uint32_t sbase = 1024, red = sbase + NST * STAGE, full0 = sbase + SMEM_BYTES - 256, empty0 = full0 + 8 * NST;
constexpr int O_NRM = 0, O_B1 = 19456, O_Z1 = 38912, O_P2 = 59392, O_ST = 3 * STAGE;
constexpr int O_RAW = 4 * STAGE;
constexpr int O_IN = 4 * STAGE, O_Y = O_IN + 19456, O_B3 = O_IN + 38912, O_MOD = O_IN + 57344;

__device__ __align__(128) const uint32_t T_TAB[5632] = {
0x3f803f80,0xbf803f80,0x3f803f80,0xbf803f80,0x3f803f80,0xbf803f80,0x3f803f80,0xbf803f80,0x3f803f80,0xbf803f80,0x3f803f80,0xbf803f80,
0x3f803f80,0xbf803f80,0x3f803f80,0xbf803f80,0x3f7f3f80,0xbdc90000,0x3f223f35,0xbf46bf35,0x3f753f7b,0xbe95be48,0x3ef13f0e,0xbf62bf55,
0x3f623f6d,0xbef1bec4,0x3e953ec4,0xbf75bf6d,0x3f463f55,0xbf22bf0e,0x3dc93e48,0xbf7fbf7b,0x3f7b3f80,0xbe480000,0xbe480000,0xbf7bbf80,
0x3f553f6d,0xbf0ebec4,0xbf0ebec4,0xbf55bf6d,0x3f0e3f35,0xbf55bf35,0xbf55bf35,0xbf0ebf35,0x3e483ec4,0xbf7bbf6d,0xbf7bbf6d,0xbe48bec4,
0x3f753f80,0xbe950000,0xbf62bf35,0xbef1bf35,0x3f223f55,0xbf46bf0e,0xbf7fbf7b,0x3dc9be48,0x3dc93ec4,0xbf7fbf6d,0xbf46bf6d,0x3f223ec4,
0xbef1be48,0xbf62bf7b,0xbe95bf0e,0x3f753f55,0x3f6d3f80,0xbec40000,0xbf6dbf80,0x3ec40000,0x3ec43f35,0xbf6dbf35,0xbec4bf35,0x3f6d3f35,
0xbec40000,0xbf6dbf80,0x3ec40000,0x3f6d3f80,0xbf6dbf35,0xbec4bf35,0x3f6d3f35,0x3ec43f35,0x3f623f80,0xbef10000,0xbe95bf35,0x3f753f35,
0x3dc93f0e,0xbf7fbf55,0x3f223e48,0x3f463f7b,0xbf46bec4,0xbf22bf6d,0x3f7f3f6d,0xbdc93ec4,0xbf75bf7b,0x3e95be48,0x3ef13f55,0xbf62bf0e,
0x3f553f80,0xbf0e0000,0x3f0e0000,0x3f553f80,0xbe483ec4,0xbf7bbf6d,0x3f7b3f6d,0xbe483ec4,0xbf7bbf35,0xbe48bf35,0x3e483f35,0xbf7bbf35,
0xbf0ebf6d,0x3f553ec4,0xbf55bec4,0xbf0ebf6d,0x3f463f80,0xbf220000,0x3f7f3f35,0x3dc93f35,0xbef13e48,0xbf62bf7b,0x3e953f55,0xbf75bf0e,
0xbf75bf6d,0x3e95bec4,0xbf62bec4,0xbef1bf6d,0x3dc9bf0e,0x3f7f3f55,0xbf22bf7b,0x3f463e48,0x3f353f80,0xbf350000,0x3f353f80,0xbf350000,
0xbf350000,0xbf35bf80,0xbf350000,0xbf35bf80,0xbf35bf80,0x3f350000,0xbf35bf80,0x3f350000,0x3f350000,0x3f353f80,0x3f350000,0x3f353f80,
0x3f223f80,0xbf460000,0xbdc93f35,0xbf7fbf35,0xbf62be48,0xbef1bf7b,0xbf75bf55,0x3e95bf0e,0xbe95bf6d,0x3f753ec4,0x3ef1bec4,0x3f623f6d,
0x3f7f3f0e,0x3dc93f55,0x3f463f7b,0xbf223e48,0x3f0e3f80,0xbf550000,0xbf550000,0xbf0ebf80,0xbf7bbec4,0xbe48bf6d,0xbe48bf6d,0x3f7b3ec4,
0x3e48bf35,0x3f7b3f35,0x3f7b3f35,0xbe483f35,0x3f553f6d,0xbf0e3ec4,0xbf0e3ec4,0xbf55bf6d,0x3ef13f80,0xbf620000,0xbf75bf35,0x3e95bf35,
0xbf7fbf0e,0x3dc9bf55,0x3f46be48,0x3f223f7b,0x3f22bec4,0x3f463f6d,0x3dc93f6d,0xbf7fbec4,0x3e953f7b,0xbf75be48,0xbf62bf55,0x3ef1bf0e,
0x3ec43f80,0xbf6d0000,0xbec4bf80,0x3f6d0000,0xbf6dbf35,0x3ec4bf35,0x3f6d3f35,0xbec43f35,0x3f6d0000,0x3ec43f80,0xbf6d0000,0xbec4bf80,
0xbec43f35,0xbf6dbf35,0x3ec4bf35,0x3f6d3f35,0x3e953f80,0xbf750000,0x3ef1bf35,0x3f623f35,0xbf46bf55,0x3f22bf0e,0x3dc93f7b,0xbf7fbe48,
0x3f7f3ec4,0xbdc93f6d,0xbf22bf6d,0x3f46bec4,0xbf623e48,0xbef1bf7b,0x3f753f0e,0xbe953f55,0x3e483f80,0xbf7b0000,0x3f7b0000,0x3e483f80,
0xbf0ebf6d,0x3f55bec4,0xbf553ec4,0xbf0ebf6d,0x3f553f35,0xbf0e3f35,0x3f0ebf35,0x3f553f35,0xbf7bbec4,0x3e48bf6d,0xbe483f6d,0xbf7bbec4,
0x3dc93f80,0xbf7f0000,0x3f463f35,0xbf223f35,0xbe95bf7b,0x3f75be48,0xbf62bf0e,0x3ef1bf55,0x3ef13f6d,0xbf623ec4,0x3f753ec4,0xbe953f6d,
0xbf22bf55,0x3f46bf0e,0xbf7fbe48,0x3dc9bf7b,0x3f80,0xbf800000,0x3f80,0xbf800000,0xbf80,0x3f800000,0xbf80,0x3f800000,
0x3f80,0xbf800000,0x3f80,0xbf800000,0xbf80,0x3f800000,0xbf80,0x3f800000,0xbdc93f80,0xbf7f0000,0xbf463f35,0xbf22bf35,
0x3e95bf7b,0x3f753e48,0x3f62bf0e,0x3ef13f55,0xbef13f6d,0xbf62bec4,0xbf753ec4,0xbe95bf6d,0x3f22bf55,0x3f463f0e,0x3f7fbe48,0x3dc93f7b,
0xbe483f80,0xbf7b0000,0xbf7b0000,0x3e48bf80,0x3f0ebf6d,0x3f553ec4,0x3f553ec4,0xbf0e3f6d,0xbf553f35,0xbf0ebf35,0xbf0ebf35,0x3f55bf35,
0x3f7bbec4,0x3e483f6d,0x3e483f6d,0xbf7b3ec4,0xbe953f80,0xbf750000,0xbef1bf35,0x3f62bf35,0x3f46bf55,0x3f223f0e,0xbdc93f7b,0xbf7f3e48,
0xbf7f3ec4,0xbdc9bf6d,0x3f22bf6d,0x3f463ec4,0x3f623e48,0xbef13f7b,0xbf753f0e,0xbe95bf55,0xbec43f80,0xbf6d0000,0x3ec4bf80,0x3f6d0000,
0x3f6dbf35,0x3ec43f35,0xbf6d3f35,0xbec4bf35,0xbf6d0000,0x3ec4bf80,0x3f6d0000,0xbec43f80,0x3ec43f35,0xbf6d3f35,0xbec4bf35,0x3f6dbf35,
0xbef13f80,0xbf620000,0x3f75bf35,0x3e953f35,0x3f7fbf0e,0x3dc93f55,0xbf46be48,0x3f22bf7b,0xbf22bec4,0x3f46bf6d,0xbdc93f6d,0xbf7f3ec4,
0xbe953f7b,0xbf753e48,0x3f62bf55,0x3ef13f0e,0xbf0e3f80,0xbf550000,0x3f550000,0xbf0e3f80,0x3f7bbec4,0xbe483f6d,0x3e48bf6d,0x3f7bbec4,
0xbe48bf35,0x3f7bbf35,0xbf7b3f35,0xbe48bf35,0xbf553f6d,0xbf0ebec4,0x3f0e3ec4,0xbf553f6d,0xbf223f80,0xbf460000,0x3dc93f35,0xbf7f3f35,
0x3f62be48,0xbef13f7b,0x3f75bf55,0x3e953f0e,0x3e95bf6d,0x3f75bec4,0xbef1bec4,0x3f62bf6d,0xbf7f3f0e,0x3dc9bf55,0xbf463f7b,0xbf22be48,
0xbf353f80,0xbf350000,0xbf353f80,0xbf350000,0x3f350000,0xbf353f80,0x3f350000,0xbf353f80,0x3f35bf80,0x3f350000,0x3f35bf80,0x3f350000,
0xbf350000,0x3f35bf80,0xbf350000,0x3f35bf80,0xbf463f80,0xbf220000,0xbf7f3f35,0x3dc9bf35,0x3ef13e48,0xbf623f7b,0xbe953f55,0xbf753f0e,
0x3f75bf6d,0x3e953ec4,0x3f62bec4,0xbef13f6d,0xbdc9bf0e,0x3f7fbf55,0x3f22bf7b,0x3f46be48,0xbf553f80,0xbf0e0000,0xbf0e0000,0x3f55bf80,
0x3e483ec4,0xbf7b3f6d,0xbf7b3f6d,0xbe48bec4,0x3f7bbf35,0xbe483f35,0xbe483f35,0xbf7b3f35,0x3f0ebf6d,0x3f55bec4,0x3f55bec4,0xbf0e3f6d,
0xbf623f80,0xbef10000,0x3e95bf35,0x3f75bf35,0xbdc93f0e,0xbf7f3f55,0xbf223e48,0x3f46bf7b,0x3f46bec4,0xbf223f6d,0xbf7f3f6d,0xbdc9bec4,
0x3f75bf7b,0x3e953e48,0xbef13f55,0xbf623f0e,0xbf6d3f80,0xbec40000,0x3f6dbf80,0x3ec40000,0xbec43f35,0xbf6d3f35,0x3ec4bf35,0x3f6dbf35,
0x3ec40000,0xbf6d3f80,0xbec40000,0x3f6dbf80,0x3f6dbf35,0xbec43f35,0xbf6d3f35,0x3ec4bf35,0xbf753f80,0xbe950000,0x3f62bf35,0xbef13f35,
0xbf223f55,0xbf463f0e,0x3f7fbf7b,0x3dc93e48,0xbdc93ec4,0xbf7f3f6d,0x3f46bf6d,0x3f22bec4,0x3ef1be48,0xbf623f7b,0x3e95bf0e,0x3f75bf55,
0xbf7b3f80,0xbe480000,0x3e480000,0xbf7b3f80,0xbf553f6d,0xbf0e3ec4,0x3f0ebec4,0xbf553f6d,0xbf0e3f35,0xbf553f35,0x3f55bf35,0xbf0e3f35,
0xbe483ec4,0xbf7b3f6d,0x3f7bbf6d,0xbe483ec4,0xbf7f3f80,0xbdc90000,0xbf223f35,0xbf463f35,0xbf753f7b,0xbe953e48,0xbef13f0e,0xbf623f55,
0xbf623f6d,0xbef13ec4,0xbe953ec4,0xbf753f6d,0xbf463f55,0xbf223f0e,0xbdc93e48,0xbf7f3f7b,0x3f803f80,0xbf803f80,0x3f803f80,0xbf803f80,
0x3f803f80,0xbf803f80,0x3f803f80,0xbf803f80,0x3f803f80,0xbf803f80,0x3f803f80,0xbf803f80,0x3f803f80,0xbf803f80,0x3f803f80,0xbf803f80,
0xbdc90000,0xbf7fbf80,0xbf46bf35,0xbf22bf35,0xbe95be48,0xbf75bf7b,0xbf62bf55,0xbef1bf0e,0xbef1bec4,0xbf62bf6d,0xbf75bf6d,0xbe95bec4,
0xbf22bf0e,0xbf46bf55,0xbf7fbf7b,0xbdc9be48,0xbf7bbf80,0x3e480000,0x3e480000,0x3f7b3f80,0xbf55bf6d,0x3f0e3ec4,0x3f0e3ec4,0x3f553f6d,
0xbf0ebf35,0x3f553f35,0x3f553f35,0x3f0e3f35,0xbe48bec4,0x3f7b3f6d,0x3f7b3f6d,0x3e483ec4,0x3e950000,0x3f753f80,0x3ef13f35,0xbf62bf35,
0x3f463f0e,0x3f223f55,0xbdc93e48,0xbf7fbf7b,0x3f7f3f6d,0x3dc93ec4,0xbf22bec4,0xbf46bf6d,0x3f623f7b,0xbef1be48,0xbf75bf55,0xbe95bf0e,
0x3f6d3f80,0xbec40000,0xbf6dbf80,0x3ec40000,0x3ec43f35,0xbf6dbf35,0xbec4bf35,0x3f6d3f35,0xbec40000,0xbf6dbf80,0x3ec40000,0x3f6d3f80,
0xbf6dbf35,0xbec4bf35,0x3f6d3f35,0x3ec43f35,0xbef10000,0xbf62bf80,0x3f753f35,0x3e953f35,0xbf7fbf55,0xbdc9bf0e,0x3f463f7b,0xbf22be48,
0xbf22bf6d,0x3f463ec4,0xbdc93ec4,0xbf7fbf6d,0x3e95be48,0x3f753f7b,0xbf62bf0e,0xbef1bf55,0xbf55bf80,0x3f0e0000,0xbf0e0000,0xbf55bf80,
0x3e48bec4,0x3f7b3f6d,0xbf7bbf6d,0x3e48bec4,0x3f7b3f35,0x3e483f35,0xbe48bf35,0x3f7b3f35,0x3f0e3f6d,0xbf55bec4,0x3f553ec4,0x3f0e3f6d,
0x3f220000,0x3f463f80,0xbdc9bf35,0x3f7f3f35,0x3f623f7b,0xbef13e48,0x3f753f0e,0x3e953f55,0xbe953ec4,0xbf75bf6d,0x3ef13f6d,0xbf62bec4,
0xbf7fbf55,0x3dc9bf0e,0xbf46be48,0xbf22bf7b,0x3f353f80,0xbf350000,0x3f353f80,0xbf350000,0xbf350000,0xbf35bf80,0xbf350000,0xbf35bf80,
0xbf35bf80,0x3f350000,0xbf35bf80,0x3f350000,0x3f350000,0x3f353f80,0x3f350000,0x3f353f80,0xbf460000,0xbf22bf80,0xbf7fbf35,0x3dc9bf35,
0xbef1bf7b,0x3f623e48,0x3e95bf0e,0x3f753f55,0x3f753ec4,0x3e953f6d,0x3f623f6d,0xbef13ec4,0x3dc93f55,0xbf7fbf0e,0xbf223e48,0xbf46bf7b,
0xbf0ebf80,0x3f550000,0x3f550000,0x3f0e3f80,0x3f7b3ec4,0x3e483f6d,0x3e483f6d,0xbf7bbec4,0xbe483f35,0xbf7bbf35,0xbf7bbf35,0x3e48bf35,
0xbf55bf6d,0x3f0ebec4,0x3f0ebec4,0x3f553f6d,0x3f620000,0x3ef13f80,0xbe953f35,0xbf75bf35,0xbdc93f55,0xbf7fbf0e,0xbf22bf7b,0x3f46be48,
0xbf46bf6d,0x3f22bec4,0x3f7f3ec4,0x3dc93f6d,0x3f753e48,0x3e953f7b,0xbef13f0e,0xbf62bf55,0x3ec43f80,0xbf6d0000,0xbec4bf80,0x3f6d0000,
0xbf6dbf35,0x3ec4bf35,0x3f6d3f35,0xbec43f35,0x3f6d0000,0x3ec43f80,0xbf6d0000,0xbec4bf80,0xbec43f35,0xbf6dbf35,0x3ec4bf35,0x3f6d3f35,
0xbf750000,0xbe95bf80,0x3f623f35,0xbef13f35,0x3f22bf0e,0x3f463f55,0xbf7fbe48,0xbdc9bf7b,0xbdc93f6d,0xbf7fbec4,0x3f46bec4,0x3f223f6d,
0xbef1bf7b,0x3f62be48,0xbe953f55,0xbf75bf0e,0xbe48bf80,0x3f7b0000,0xbf7b0000,0xbe48bf80,0x3f0e3f6d,0xbf553ec4,0x3f55bec4,0x3f0e3f6d,
0xbf55bf35,0x3f0ebf35,0xbf0e3f35,0xbf55bf35,0x3f7b3ec4,0xbe483f6d,0x3e48bf6d,0x3f7b3ec4,0x3f7f0000,0x3dc93f80,0x3f22bf35,0x3f463f35,
0xbf753e48,0xbe95bf7b,0xbef13f55,0xbf62bf0e,0x3f62bec4,0x3ef13f6d,0x3e95bf6d,0x3f753ec4,0xbf463f0e,0xbf22bf55,0xbdc93f7b,0xbf7fbe48,
0x3f80,0xbf800000,0x3f80,0xbf800000,0xbf80,0x3f800000,0xbf80,0x3f800000,0x3f80,0xbf800000,0x3f80,0xbf800000,
0xbf80,0x3f800000,0xbf80,0x3f800000,0xbf7f0000,0x3dc9bf80,0xbf22bf35,0x3f46bf35,0x3f753e48,0xbe953f7b,0x3ef13f55,0xbf623f0e,
0xbf62bec4,0x3ef1bf6d,0xbe95bf6d,0x3f75bec4,0x3f463f0e,0xbf223f55,0x3dc93f7b,0xbf7f3e48,0x3e48bf80,0x3f7b0000,0x3f7b0000,0xbe483f80,
0xbf0e3f6d,0xbf55bec4,0xbf55bec4,0x3f0ebf6d,0x3f55bf35,0x3f0e3f35,0x3f0e3f35,0xbf553f35,0xbf7b3ec4,0xbe48bf6d,0xbe48bf6d,0x3f7bbec4,
0x3f750000,0xbe953f80,0xbf623f35,0xbef1bf35,0xbf22bf0e,0x3f46bf55,0x3f7fbe48,0xbdc93f7b,0x3dc93f6d,0xbf7f3ec4,0xbf46bec4,0x3f22bf6d,
0x3ef1bf7b,0x3f623e48,0x3e953f55,0xbf753f0e,0xbec43f80,0xbf6d0000,0x3ec4bf80,0x3f6d0000,0x3f6dbf35,0x3ec43f35,0xbf6d3f35,0xbec4bf35,
0xbf6d0000,0x3ec4bf80,0x3f6d0000,0xbec43f80,0x3ec43f35,0xbf6d3f35,0xbec4bf35,0x3f6dbf35,0xbf620000,0x3ef1bf80,0x3e953f35,0xbf753f35,
0x3dc93f55,0xbf7f3f0e,0x3f22bf7b,0x3f463e48,0x3f46bf6d,0x3f223ec4,0xbf7f3ec4,0x3dc9bf6d,0xbf753e48,0x3e95bf7b,0x3ef13f0e,0xbf623f55,
0x3f0ebf80,0x3f550000,0xbf550000,0x3f0ebf80,0xbf7b3ec4,0x3e48bf6d,0xbe483f6d,0xbf7b3ec4,0x3e483f35,0xbf7b3f35,0x3f7bbf35,0x3e483f35,
0x3f55bf6d,0x3f0e3ec4,0xbf0ebec4,0x3f55bf6d,0x3f460000,0xbf223f80,0x3f7fbf35,0x3dc93f35,0x3ef1bf7b,0x3f62be48,0xbe95bf0e,0x3f75bf55,
0xbf753ec4,0x3e95bf6d,0xbf623f6d,0xbef1bec4,0xbdc93f55,0xbf7f3f0e,0x3f223e48,0xbf463f7b,0xbf353f80,0xbf350000,0xbf353f80,0xbf350000,
0x3f350000,0xbf353f80,0x3f350000,0xbf353f80,0x3f35bf80,0x3f350000,0x3f35bf80,0x3f350000,0xbf350000,0x3f35bf80,0xbf350000,0x3f35bf80,
0xbf220000,0x3f46bf80,0x3dc9bf35,0x3f7fbf35,0xbf623f7b,0xbef1be48,0xbf753f0e,0x3e95bf55,0x3e953ec4,0xbf753f6d,0xbef13f6d,0xbf623ec4,
0x3f7fbf55,0x3dc93f0e,0x3f46be48,0xbf223f7b,0x3f55bf80,0x3f0e0000,0x3f0e0000,0xbf553f80,0xbe48bec4,0x3f7bbf6d,0x3f7bbf6d,0x3e483ec4,
0xbf7b3f35,0x3e48bf35,0x3e48bf35,0x3f7bbf35,0xbf0e3f6d,0xbf553ec4,0xbf553ec4,0x3f0ebf6d,0x3ef10000,0xbf623f80,0xbf753f35,0x3e95bf35,
0x3f7fbf55,0xbdc93f0e,0xbf463f7b,0xbf223e48,0x3f22bf6d,0x3f46bec4,0x3dc93ec4,0xbf7f3f6d,0xbe95be48,0x3f75bf7b,0x3f62bf0e,0xbef13f55,
0xbf6d3f80,0xbec40000,0x3f6dbf80,0x3ec40000,0xbec43f35,0xbf6d3f35,0x3ec4bf35,0x3f6dbf35,0x3ec40000,0xbf6d3f80,0xbec40000,0x3f6dbf80,
0x3f6dbf35,0xbec43f35,0xbf6d3f35,0x3ec4bf35,0xbe950000,0x3f75bf80,0xbef13f35,0xbf623f35,0xbf463f0e,0x3f22bf55,0x3dc93e48,0xbf7f3f7b,
0xbf7f3f6d,0x3dc9bec4,0x3f22bec4,0xbf463f6d,0xbf623f7b,0xbef13e48,0x3f75bf55,0xbe953f0e,0x3f7bbf80,0x3e480000,0xbe480000,0x3f7bbf80,
0x3f55bf6d,0x3f0ebec4,0xbf0e3ec4,0x3f55bf6d,0x3f0ebf35,0x3f55bf35,0xbf553f35,0x3f0ebf35,0x3e48bec4,0x3f7bbf6d,0xbf7b3f6d,0x3e48bec4,
0x3dc90000,0xbf7f3f80,0x3f46bf35,0xbf223f35,0x3e95be48,0xbf753f7b,0x3f62bf55,0xbef13f0e,0x3ef1bec4,0xbf623f6d,0x3f75bf6d,0xbe953ec4,
0x3f22bf0e,0xbf463f55,0x3f7fbf7b,0xbdc93e48,0x3f803f80,0xbf803f80,0x3f803f80,0xbf803f80,0x3f803f80,0xbf803f80,0x3f803f80,0xbf803f80,
0x3f803f80,0xbf803f80,0x3f803f80,0xbf803f80,0x3f803f80,0xbf803f80,0x3f803f80,0xbf803f80,0xbf7fbf80,0x3dc90000,0xbf22bf35,0x3f463f35,
0xbf75bf7b,0x3e953e48,0xbef1bf0e,0x3f623f55,0xbf62bf6d,0x3ef13ec4,0xbe95bec4,0x3f753f6d,0xbf46bf55,0x3f223f0e,0xbdc9be48,0x3f7f3f7b,
0x3f7b3f80,0xbe480000,0xbe480000,0xbf7bbf80,0x3f553f6d,0xbf0ebec4,0xbf0ebec4,0xbf55bf6d,0x3f0e3f35,0xbf55bf35,0xbf55bf35,0xbf0ebf35,
0x3e483ec4,0xbf7bbf6d,0xbf7bbf6d,0xbe48bec4,0xbf75bf80,0x3e950000,0x3f623f35,0x3ef13f35,0xbf22bf55,0x3f463f0e,0x3f7f3f7b,0xbdc93e48,
0xbdc9bec4,0x3f7f3f6d,0x3f463f6d,0xbf22bec4,0x3ef13e48,0x3f623f7b,0x3e953f0e,0xbf75bf55,0x3f6d3f80,0xbec40000,0xbf6dbf80,0x3ec40000,
0x3ec43f35,0xbf6dbf35,0xbec4bf35,0x3f6d3f35,0xbec40000,0xbf6dbf80,0x3ec40000,0x3f6d3f80,0xbf6dbf35,0xbec4bf35,0x3f6d3f35,0x3ec43f35,
0xbf62bf80,0x3ef10000,0x3e953f35,0xbf75bf35,0xbdc9bf0e,0x3f7f3f55,0xbf22be48,0xbf46bf7b,0x3f463ec4,0x3f223f6d,0xbf7fbf6d,0x3dc9bec4,
0x3f753f7b,0xbe953e48,0xbef1bf55,0x3f623f0e,0x3f553f80,0xbf0e0000,0x3f0e0000,0x3f553f80,0xbe483ec4,0xbf7bbf6d,0x3f7b3f6d,0xbe483ec4,
0xbf7bbf35,0xbe48bf35,0x3e483f35,0xbf7bbf35,0xbf0ebf6d,0x3f553ec4,0xbf55bec4,0xbf0ebf6d,0xbf46bf80,0x3f220000,0xbf7fbf35,0xbdc9bf35,
0x3ef1be48,0x3f623f7b,0xbe95bf55,0x3f753f0e,0x3f753f6d,0xbe953ec4,0x3f623ec4,0x3ef13f6d,0xbdc93f0e,0xbf7fbf55,0x3f223f7b,0xbf46be48,
0x3f353f80,0xbf350000,0x3f353f80,0xbf350000,0xbf350000,0xbf35bf80,0xbf350000,0xbf35bf80,0xbf35bf80,0x3f350000,0xbf35bf80,0x3f350000,
0x3f350000,0x3f353f80,0x3f350000,0x3f353f80,0xbf22bf80,0x3f460000,0x3dc9bf35,0x3f7f3f35,0x3f623e48,0x3ef13f7b,0x3f753f55,0xbe953f0e,
0x3e953f6d,0xbf75bec4,0xbef13ec4,0xbf62bf6d,0xbf7fbf0e,0xbdc9bf55,0xbf46bf7b,0x3f22be48,0x3f0e3f80,0xbf550000,0xbf550000,0xbf0ebf80,
0xbf7bbec4,0xbe48bf6d,0xbe48bf6d,0x3f7b3ec4,0x3e48bf35,0x3f7b3f35,0x3f7b3f35,0xbe483f35,0x3f553f6d,0xbf0e3ec4,0xbf0e3ec4,0xbf55bf6d,
0xbef1bf80,0x3f620000,0x3f753f35,0xbe953f35,0x3f7f3f0e,0xbdc93f55,0xbf463e48,0xbf22bf7b,0xbf223ec4,0xbf46bf6d,0xbdc9bf6d,0x3f7f3ec4,
0xbe95bf7b,0x3f753e48,0x3f623f55,0xbef13f0e,0x3ec43f80,0xbf6d0000,0xbec4bf80,0x3f6d0000,0xbf6dbf35,0x3ec4bf35,0x3f6d3f35,0xbec43f35,
0x3f6d0000,0x3ec43f80,0xbf6d0000,0xbec4bf80,0xbec43f35,0xbf6dbf35,0x3ec4bf35,0x3f6d3f35,0xbe95bf80,0x3f750000,0xbef13f35,0xbf62bf35,
0x3f463f55,0xbf223f0e,0xbdc9bf7b,0x3f7f3e48,0xbf7fbec4,0x3dc9bf6d,0x3f223f6d,0xbf463ec4,0x3f62be48,0x3ef13f7b,0xbf75bf0e,0x3e95bf55,
0x3e483f80,0xbf7b0000,0x3f7b0000,0x3e483f80,0xbf0ebf6d,0x3f55bec4,0xbf553ec4,0xbf0ebf6d,0x3f553f35,0xbf0e3f35,0x3f0ebf35,0x3f553f35,
0xbf7bbec4,0x3e48bf6d,0xbe483f6d,0xbf7bbec4,0xbdc9bf80,0x3f7f0000,0xbf46bf35,0x3f22bf35,0x3e953f7b,0xbf753e48,0x3f623f0e,0xbef13f55,
0xbef1bf6d,0x3f62bec4,0xbf75bec4,0x3e95bf6d,0x3f223f55,0xbf463f0e,0x3f7f3e48,0xbdc93f7b,0x3f80,0xbf800000,0x3f80,0xbf800000,
0xbf80,0x3f800000,0xbf80,0x3f800000,0x3f80,0xbf800000,0x3f80,0xbf800000,0xbf80,0x3f800000,0xbf80,0x3f800000,
0x3dc9bf80,0x3f7f0000,0x3f46bf35,0x3f223f35,0xbe953f7b,0xbf75be48,0xbf623f0e,0xbef1bf55,0x3ef1bf6d,0x3f623ec4,0x3f75bec4,0x3e953f6d,
0xbf223f55,0xbf46bf0e,0xbf7f3e48,0xbdc9bf7b,0xbe483f80,0xbf7b0000,0xbf7b0000,0x3e48bf80,0x3f0ebf6d,0x3f553ec4,0x3f553ec4,0xbf0e3f6d,
0xbf553f35,0xbf0ebf35,0xbf0ebf35,0x3f55bf35,0x3f7bbec4,0x3e483f6d,0x3e483f6d,0xbf7b3ec4,0x3e95bf80,0x3f750000,0x3ef13f35,0xbf623f35,
0xbf463f55,0xbf22bf0e,0x3dc9bf7b,0x3f7fbe48,0x3f7fbec4,0x3dc93f6d,0xbf223f6d,0xbf46bec4,0xbf62be48,0x3ef1bf7b,0x3f75bf0e,0x3e953f55,
0xbec43f80,0xbf6d0000,0x3ec4bf80,0x3f6d0000,0x3f6dbf35,0x3ec43f35,0xbf6d3f35,0xbec4bf35,0xbf6d0000,0x3ec4bf80,0x3f6d0000,0xbec43f80,
0x3ec43f35,0xbf6d3f35,0xbec4bf35,0x3f6dbf35,0x3ef1bf80,0x3f620000,0xbf753f35,0xbe95bf35,0xbf7f3f0e,0xbdc9bf55,0x3f463e48,0xbf223f7b,
0x3f223ec4,0xbf463f6d,0x3dc9bf6d,0x3f7fbec4,0x3e95bf7b,0x3f75be48,0xbf623f55,0xbef1bf0e,0xbf0e3f80,0xbf550000,0x3f550000,0xbf0e3f80,
0x3f7bbec4,0xbe483f6d,0x3e48bf6d,0x3f7bbec4,0xbe48bf35,0x3f7bbf35,0xbf7b3f35,0xbe48bf35,0xbf553f6d,0xbf0ebec4,0x3f0e3ec4,0xbf553f6d,
0x3f22bf80,0x3f460000,0xbdc9bf35,0x3f7fbf35,0xbf623e48,0x3ef1bf7b,0xbf753f55,0xbe95bf0e,0xbe953f6d,0xbf753ec4,0x3ef13ec4,0xbf623f6d,
0x3f7fbf0e,0xbdc93f55,0x3f46bf7b,0x3f223e48,0xbf353f80,0xbf350000,0xbf353f80,0xbf350000,0x3f350000,0xbf353f80,0x3f350000,0xbf353f80,
0x3f35bf80,0x3f350000,0x3f35bf80,0x3f350000,0xbf350000,0x3f35bf80,0xbf350000,0x3f35bf80,0x3f46bf80,0x3f220000,0x3f7fbf35,0xbdc93f35,
0xbef1be48,0x3f62bf7b,0x3e95bf55,0x3f75bf0e,0xbf753f6d,0xbe95bec4,0xbf623ec4,0x3ef1bf6d,0x3dc93f0e,0xbf7f3f55,0xbf223f7b,0xbf463e48,
0xbf553f80,0xbf0e0000,0xbf0e0000,0x3f55bf80,0x3e483ec4,0xbf7b3f6d,0xbf7b3f6d,0xbe48bec4,0x3f7bbf35,0xbe483f35,0xbe483f35,0xbf7b3f35,
0x3f0ebf6d,0x3f55bec4,0x3f55bec4,0xbf0e3f6d,0x3f62bf80,0x3ef10000,0xbe953f35,0xbf753f35,0x3dc9bf0e,0x3f7fbf55,0x3f22be48,0xbf463f7b,
0xbf463ec4,0x3f22bf6d,0x3f7fbf6d,0x3dc93ec4,0xbf753f7b,0xbe95be48,0x3ef1bf55,0x3f62bf0e,0xbf6d3f80,0xbec40000,0x3f6dbf80,0x3ec40000,
0xbec43f35,0xbf6d3f35,0x3ec4bf35,0x3f6dbf35,0x3ec40000,0xbf6d3f80,0xbec40000,0x3f6dbf80,0x3f6dbf35,0xbec43f35,0xbf6d3f35,0x3ec4bf35,
0x3f75bf80,0x3e950000,0xbf623f35,0x3ef1bf35,0x3f22bf55,0x3f46bf0e,0xbf7f3f7b,0xbdc9be48,0x3dc9bec4,0x3f7fbf6d,0xbf463f6d,0xbf223ec4,
0xbef13e48,0x3f62bf7b,0xbe953f0e,0xbf753f55,0xbf7b3f80,0xbe480000,0x3e480000,0xbf7b3f80,0xbf553f6d,0xbf0e3ec4,0x3f0ebec4,0xbf553f6d,
0xbf0e3f35,0xbf553f35,0x3f55bf35,0xbf0e3f35,0xbe483ec4,0xbf7b3f6d,0x3f7bbf6d,0xbe483ec4,0x3f7fbf80,0x3dc90000,0x3f22bf35,0x3f46bf35,
0x3f75bf7b,0x3e95be48,0x3ef1bf0e,0x3f62bf55,0x3f62bf6d,0x3ef1bec4,0x3e95bec4,0x3f75bf6d,0x3f46bf55,0x3f22bf0e,0x3dc9be48,0x3f7fbf7b,
0x3f803f80,0xbf803f80,0x3f803f80,0xbf803f80,0x3f803f80,0xbf803f80,0x3f803f80,0xbf803f80,0x3f803f80,0xbf803f80,0x3f803f80,0xbf803f80,
0x3f803f80,0xbf803f80,0x3f803f80,0xbf803f80,0x3dc90000,0x3f7f3f80,0x3f463f35,0x3f223f35,0x3e953e48,0x3f753f7b,0x3f623f55,0x3ef13f0e,
0x3ef13ec4,0x3f623f6d,0x3f753f6d,0x3e953ec4,0x3f223f0e,0x3f463f55,0x3f7f3f7b,0x3dc93e48,0xbf7bbf80,0x3e480000,0x3e480000,0x3f7b3f80,
0xbf55bf6d,0x3f0e3ec4,0x3f0e3ec4,0x3f553f6d,0xbf0ebf35,0x3f553f35,0x3f553f35,0x3f0e3f35,0xbe48bec4,0x3f7b3f6d,0x3f7b3f6d,0x3e483ec4,
0xbe950000,0xbf75bf80,0xbef1bf35,0x3f623f35,0xbf46bf0e,0xbf22bf55,0x3dc9be48,0x3f7f3f7b,0xbf7fbf6d,0xbdc9bec4,0x3f223ec4,0x3f463f6d,
0xbf62bf7b,0x3ef13e48,0x3f753f55,0x3e953f0e,0x3f6d3f80,0xbec40000,0xbf6dbf80,0x3ec40000,0x3ec43f35,0xbf6dbf35,0xbec4bf35,0x3f6d3f35,
0xbec40000,0xbf6dbf80,0x3ec40000,0x3f6d3f80,0xbf6dbf35,0xbec4bf35,0x3f6d3f35,0x3ec43f35,0x3ef10000,0x3f623f80,0xbf75bf35,0xbe95bf35,
0x3f7f3f55,0x3dc93f0e,0xbf46bf7b,0x3f223e48,0x3f223f6d,0xbf46bec4,0x3dc9bec4,0x3f7f3f6d,0xbe953e48,0xbf75bf7b,0x3f623f0e,0x3ef13f55,
0xbf55bf80,0x3f0e0000,0xbf0e0000,0xbf55bf80,0x3e48bec4,0x3f7b3f6d,0xbf7bbf6d,0x3e48bec4,0x3f7b3f35,0x3e483f35,0xbe48bf35,0x3f7b3f35,
0x3f0e3f6d,0xbf55bec4,0x3f553ec4,0x3f0e3f6d,0xbf220000,0xbf46bf80,0x3dc93f35,0xbf7fbf35,0xbf62bf7b,0x3ef1be48,0xbf75bf0e,0xbe95bf55,
0x3e95bec4,0x3f753f6d,0xbef1bf6d,0x3f623ec4,0x3f7f3f55,0xbdc93f0e,0x3f463e48,0x3f223f7b,0x3f353f80,0xbf350000,0x3f353f80,0xbf350000,
0xbf350000,0xbf35bf80,0xbf350000,0xbf35bf80,0xbf35bf80,0x3f350000,0xbf35bf80,0x3f350000,0x3f350000,0x3f353f80,0x3f350000,0x3f353f80,
0x3f460000,0x3f223f80,0x3f7f3f35,0xbdc93f35,0x3ef13f7b,0xbf62be48,0xbe953f0e,0xbf75bf55,0xbf75bec4,0xbe95bf6d,0xbf62bf6d,0x3ef1bec4,
0xbdc9bf55,0x3f7f3f0e,0x3f22be48,0x3f463f7b,0xbf0ebf80,0x3f550000,0x3f550000,0x3f0e3f80,0x3f7b3ec4,0x3e483f6d,0x3e483f6d,0xbf7bbec4,
0xbe483f35,0xbf7bbf35,0xbf7bbf35,0x3e48bf35,0xbf55bf6d,0x3f0ebec4,0x3f0ebec4,0x3f553f6d,0xbf620000,0xbef1bf80,0x3e95bf35,0x3f753f35,
0x3dc9bf55,0x3f7f3f0e,0x3f223f7b,0xbf463e48,0x3f463f6d,0xbf223ec4,0xbf7fbec4,0xbdc9bf6d,0xbf75be48,0xbe95bf7b,0x3ef1bf0e,0x3f623f55,
0x3ec43f80,0xbf6d0000,0xbec4bf80,0x3f6d0000,0xbf6dbf35,0x3ec4bf35,0x3f6d3f35,0xbec43f35,0x3f6d0000,0x3ec43f80,0xbf6d0000,0xbec4bf80,
0xbec43f35,0xbf6dbf35,0x3ec4bf35,0x3f6d3f35,0x3f750000,0x3e953f80,0xbf62bf35,0x3ef1bf35,0xbf223f0e,0xbf46bf55,0x3f7f3e48,0x3dc93f7b,
0x3dc9bf6d,0x3f7f3ec4,0xbf463ec4,0xbf22bf6d,0x3ef13f7b,0xbf623e48,0x3e95bf55,0x3f753f0e,0xbe48bf80,0x3f7b0000,0xbf7b0000,0xbe48bf80,
0x3f0e3f6d,0xbf553ec4,0x3f55bec4,0x3f0e3f6d,0xbf55bf35,0x3f0ebf35,0xbf0e3f35,0xbf55bf35,0x3f7b3ec4,0xbe483f6d,0x3e48bf6d,0x3f7b3ec4,
0xbf7f0000,0xbdc9bf80,0xbf223f35,0xbf46bf35,0x3f75be48,0x3e953f7b,0x3ef1bf55,0x3f623f0e,0xbf623ec4,0xbef1bf6d,0xbe953f6d,0xbf75bec4,
0x3f46bf0e,0x3f223f55,0x3dc9bf7b,0x3f7f3e48,0x3f80,0xbf800000,0x3f80,0xbf800000,0xbf80,0x3f800000,0xbf80,0x3f800000,
0x3f80,0xbf800000,0x3f80,0xbf800000,0xbf80,0x3f800000,0xbf80,0x3f800000,0x3f7f0000,0xbdc93f80,0x3f223f35,0xbf463f35,
0xbf75be48,0x3e95bf7b,0xbef1bf55,0x3f62bf0e,0x3f623ec4,0xbef13f6d,0x3e953f6d,0xbf753ec4,0xbf46bf0e,0x3f22bf55,0xbdc9bf7b,0x3f7fbe48,
0x3e48bf80,0x3f7b0000,0x3f7b0000,0xbe483f80,0xbf0e3f6d,0xbf55bec4,0xbf55bec4,0x3f0ebf6d,0x3f55bf35,0x3f0e3f35,0x3f0e3f35,0xbf553f35,
0xbf7b3ec4,0xbe48bf6d,0xbe48bf6d,0x3f7bbec4,0xbf750000,0x3e95bf80,0x3f62bf35,0x3ef13f35,0x3f223f0e,0xbf463f55,0xbf7f3e48,0x3dc9bf7b,
0xbdc9bf6d,0x3f7fbec4,0x3f463ec4,0xbf223f6d,0xbef13f7b,0xbf62be48,0xbe95bf55,0x3f75bf0e,0xbec43f80,0xbf6d0000,0x3ec4bf80,0x3f6d0000,
0x3f6dbf35,0x3ec43f35,0xbf6d3f35,0xbec4bf35,0xbf6d0000,0x3ec4bf80,0x3f6d0000,0xbec43f80,0x3ec43f35,0xbf6d3f35,0xbec4bf35,0x3f6dbf35,
0x3f620000,0xbef13f80,0xbe95bf35,0x3f75bf35,0xbdc9bf55,0x3f7fbf0e,0xbf223f7b,0xbf46be48,0xbf463f6d,0xbf22bec4,0x3f7fbec4,0xbdc93f6d,
0x3f75be48,0xbe953f7b,0xbef1bf0e,0x3f62bf55,0x3f0ebf80,0x3f550000,0xbf550000,0x3f0ebf80,0xbf7b3ec4,0x3e48bf6d,0xbe483f6d,0xbf7b3ec4,
0x3e483f35,0xbf7b3f35,0x3f7bbf35,0x3e483f35,0x3f55bf6d,0x3f0e3ec4,0xbf0ebec4,0x3f55bf6d,0xbf460000,0x3f22bf80,0xbf7f3f35,0xbdc9bf35,
0xbef13f7b,0xbf623e48,0x3e953f0e,0xbf753f55,0x3f75bec4,0xbe953f6d,0x3f62bf6d,0x3ef13ec4,0x3dc9bf55,0x3f7fbf0e,0xbf22be48,0x3f46bf7b,
0xbf353f80,0xbf350000,0xbf353f80,0xbf350000,0x3f350000,0xbf353f80,0x3f350000,0xbf353f80,0x3f35bf80,0x3f350000,0x3f35bf80,0x3f350000,
0xbf350000,0x3f35bf80,0xbf350000,0x3f35bf80,0x3f220000,0xbf463f80,0xbdc93f35,0xbf7f3f35,0x3f62bf7b,0x3ef13e48,0x3f75bf0e,0xbe953f55,
0xbe95bec4,0x3f75bf6d,0x3ef1bf6d,0x3f62bec4,0xbf7f3f55,0xbdc9bf0e,0xbf463e48,0x3f22bf7b,0x3f55bf80,0x3f0e0000,0x3f0e0000,0xbf553f80,
0xbe48bec4,0x3f7bbf6d,0x3f7bbf6d,0x3e483ec4,0xbf7b3f35,0x3e48bf35,0x3e48bf35,0x3f7bbf35,0xbf0e3f6d,0xbf553ec4,0xbf553ec4,0x3f0ebf6d,
0xbef10000,0x3f62bf80,0x3f75bf35,0xbe953f35,0xbf7f3f55,0x3dc9bf0e,0x3f46bf7b,0x3f22be48,0xbf223f6d,0xbf463ec4,0xbdc9bec4,0x3f7fbf6d,
0x3e953e48,0xbf753f7b,0xbf623f0e,0x3ef1bf55,0xbf6d3f80,0xbec40000,0x3f6dbf80,0x3ec40000,0xbec43f35,0xbf6d3f35,0x3ec4bf35,0x3f6dbf35,
0x3ec40000,0xbf6d3f80,0xbec40000,0x3f6dbf80,0x3f6dbf35,0xbec43f35,0xbf6d3f35,0x3ec4bf35,0x3e950000,0xbf753f80,0x3ef1bf35,0x3f62bf35,
0x3f46bf0e,0xbf223f55,0xbdc9be48,0x3f7fbf7b,0x3f7fbf6d,0xbdc93ec4,0xbf223ec4,0x3f46bf6d,0x3f62bf7b,0x3ef1be48,0xbf753f55,0x3e95bf0e,
0x3f7bbf80,0x3e480000,0xbe480000,0x3f7bbf80,0x3f55bf6d,0x3f0ebec4,0xbf0e3ec4,0x3f55bf6d,0x3f0ebf35,0x3f55bf35,0xbf553f35,0x3f0ebf35,
0x3e48bec4,0x3f7bbf6d,0xbf7b3f6d,0x3e48bec4,0xbdc90000,0x3f7fbf80,0xbf463f35,0x3f22bf35,0xbe953e48,0x3f75bf7b,0xbf623f55,0x3ef1bf0e,
0xbef13ec4,0x3f62bf6d,0xbf753f6d,0x3e95bec4,0xbf223f0e,0x3f46bf55,0xbf7f3f7b,0x3dc9be48,0x40003f80,0x3fb53f80,0x3f80,0xbfb53f80,
0x40004000,0xbfb50000,0x0,0xbfb5c000,0x40004000,0xbfb5c000,0x0,0x3fb50000,0x40004000,0x3fb50000,0x0,0x3fb54000,
0x3fff3f80,0x3fa23f80,0xbe49bf80,0xbfc6bf80,0x3ff53ffb,0xbfe2bec8,0xbf15bec8,0xbf71bffb,0x3fe23fed,0xbf15bfed,0xbf71bf44,0x3ff53f44,
0x3fc63fd5,0x3fff3f8e,0xbfa2bf8e,0x3e493fd5,0x3ffb3f80,0x3f8e3f80,0xbec83f80,0xbfd53f80,0x3fd53fed,0xbffbbf44,0xbf8ebf44,0xbec8bfed,
0x3f8e3fb5,0x3ec8bfb5,0xbfd5bfb5,0x3ffb3fb5,0x3ec83f44,0x3fd53fed,0xbffbbfed,0xbf8e3f44,0x3ff53f80,0x3f713f80,0xbf15bf80,0xbfe2bf80,
0x3fa23fd5,0xbfffbf8e,0xbfc6bf8e,0x3e49bfd5,0x3e493f44,0x3fa2bf44,0xbfffbfed,0x3fc63fed,0xbf71bec8,0x3f153ffb,0xbfe2bffb,0xbff5bec8,
0x3fed3f80,0x3f443f80,0xbf443f80,0xbfed3f80,0x3f443fb5,0xbfedbfb5,0xbfedbfb5,0x3f44bfb5,0xbf440000,0x3fed0000,0xbfedc000,0x3f444000,
0xbfedbfb5,0xbf443fb5,0xbf44bfb5,0xbfedbfb5,0x3fe23f80,0x3f153f80,0xbf71bf80,0xbff5bf80,0x3e493f8e,0xbfc6bfd5,0xbfffbfd5,0x3fa2bf8e,
0xbfc6bf44,0x3fff3f44,0xbfa2bfed,0xbe493fed,0xbff5bffb,0xbfe23ec8,0x3f15bec8,0xbf71bffb,0x3fd53f80,0x3ec83f80,0xbf8e3f80,0xbffb3f80,
0xbec83f44,0xbf8ebfed,0xbffbbfed,0x3fd5bf44,0xbffbbfb5,0x3fd53fb5,0xbec8bfb5,0xbf8e3fb5,0xbf8ebfed,0xbffbbf44,0x3fd53f44,0x3ec8bfed,
0x3fc63f80,0x3e493f80,0xbfa2bf80,0xbfffbf80,0xbf713ec8,0xbf15bffb,0xbfe2bffb,0x3ff5bec8,0xbff5bfed,0x3f713fed,0x3f15bf44,0xbfe23f44,
0x3e49bf8e,0xbfa2bfd5,0x3fff3fd5,0x3fc6bf8e,0x3f80,0xbfb53f80,0xc0003f80,0xbfb53f80,0xc000,0x3fb50000,0x40000000,0xbfb54000,
0x4000,0x3fb5c000,0xc0000000,0x3fb50000,0xc000,0xbfb50000,0x40000000,0x3fb5c000,0xbe493f80,0xbfc63f80,0xbfffbf80,0xbfa2bf80,
0x3f15bffb,0x3f713ec8,0x3ff53ec8,0xbfe23ffb,0xbf713fed,0x3ff5bfed,0xbfe2bf44,0x3f153f44,0x3fa2bfd5,0xbe49bf8e,0x3fc63f8e,0x3fffbfd5,
0xbec83f80,0xbfd53f80,0xbffb3f80,0xbf8e3f80,0x3f8ebfed,0x3ec83f44,0x3fd53f44,0xbffb3fed,0xbfd53fb5,0x3ffbbfb5,0xbf8ebfb5,0xbec83fb5,
0x3ffbbf44,0x3f8ebfed,0x3ec83fed,0x3fd5bf44,0xbf153f80,0xbfe23f80,0xbff5bf80,0xbf71bf80,0x3fc6bfd5,0xbe493f8e,0x3fa23f8e,0xbfff3fd5,
0xbfff3f44,0x3fc6bf44,0xbe49bfed,0xbfa23fed,0x3fe23ec8,0x3ff5bffb,0xbf713ffb,0x3f153ec8,0xbf443f80,0xbfed3f80,0xbfed3f80,0xbf443f80,
0x3fedbfb5,0xbf443fb5,0x3f443fb5,0xbfed3fb5,0xbfed0000,0x3f440000,0x3f44c000,0xbfed4000,0x3f443fb5,0x3fedbfb5,0xbfed3fb5,0xbf443fb5,
0xbf713f80,0xbff53f80,0xbfe2bf80,0xbf15bf80,0x3fffbf8e,0xbfa23fd5,0x3e493fd5,0xbfc63f8e,0xbfa2bf44,0xbe493f44,0x3fc6bfed,0xbfff3fed,
0xbf153ffb,0x3f71bec8,0xbff53ec8,0xbfe23ffb,0xbf8e3f80,0xbffb3f80,0xbfd53f80,0xbec83f80,0x3ffbbf44,0xbfd53fed,0xbec83fed,0xbf8e3f44,
0xbec8bfb5,0xbf8e3fb5,0x3ffbbfb5,0xbfd53fb5,0xbfd53fed,0xbec83f44,0xbf8ebf44,0xbffb3fed,0xbfa23f80,0xbfff3f80,0xbfc6bf80,0xbe49bf80,
0x3fe2bec8,0xbff53ffb,0xbf713ffb,0xbf153ec8,0x3f15bfed,0xbfe23fed,0x3ff5bf44,0xbf713f44,0xbfff3f8e,0xbfc63fd5,0x3e49bfd5,0xbfa23f8e,
0xc0003f80,0xbfb53f80,0x3f80,0x3fb53f80,0xc0004000,0x3fb50000,0x0,0x3fb5c000,0xc0004000,0x3fb5c000,0x0,0xbfb50000,
0xc0004000,0xbfb50000,0x0,0xbfb54000,0xbfff3f80,0xbfa23f80,0x3e49bf80,0x3fc6bf80,0xbff53ffb,0x3fe2bec8,0x3f15bec8,0x3f71bffb,
0xbfe23fed,0x3f15bfed,0x3f71bf44,0xbff53f44,0xbfc63fd5,0xbfff3f8e,0x3fa2bf8e,0xbe493fd5,0xbffb3f80,0xbf8e3f80,0x3ec83f80,0x3fd53f80,
0xbfd53fed,0x3ffbbf44,0x3f8ebf44,0x3ec8bfed,0xbf8e3fb5,0xbec8bfb5,0x3fd5bfb5,0xbffb3fb5,0xbec83f44,0xbfd53fed,0x3ffbbfed,0x3f8e3f44,
0xbff53f80,0xbf713f80,0x3f15bf80,0x3fe2bf80,0xbfa23fd5,0x3fffbf8e,0x3fc6bf8e,0xbe49bfd5,0xbe493f44,0xbfa2bf44,0x3fffbfed,0xbfc63fed,
0x3f71bec8,0xbf153ffb,0x3fe2bffb,0x3ff5bec8,0xbfed3f80,0xbf443f80,0x3f443f80,0x3fed3f80,0xbf443fb5,0x3fedbfb5,0x3fedbfb5,0xbf44bfb5,
0x3f440000,0xbfed0000,0x3fedc000,0xbf444000,0x3fedbfb5,0x3f443fb5,0x3f44bfb5,0x3fedbfb5,0xbfe23f80,0xbf153f80,0x3f71bf80,0x3ff5bf80,
0xbe493f8e,0x3fc6bfd5,0x3fffbfd5,0xbfa2bf8e,0x3fc6bf44,0xbfff3f44,0x3fa2bfed,0x3e493fed,0x3ff5bffb,0x3fe23ec8,0xbf15bec8,0x3f71bffb,
0xbfd53f80,0xbec83f80,0x3f8e3f80,0x3ffb3f80,0x3ec83f44,0x3f8ebfed,0x3ffbbfed,0xbfd5bf44,0x3ffbbfb5,0xbfd53fb5,0x3ec8bfb5,0x3f8e3fb5,
0x3f8ebfed,0x3ffbbf44,0xbfd53f44,0xbec8bfed,0xbfc63f80,0xbe493f80,0x3fa2bf80,0x3fffbf80,0x3f713ec8,0x3f15bffb,0x3fe2bffb,0xbff5bec8,
0x3ff5bfed,0xbf713fed,0xbf15bf44,0x3fe23f44,0xbe49bf8e,0x3fa2bfd5,0xbfff3fd5,0xbfc6bf8e,0x3f80,0x3fb53f80,0x40003f80,0x3fb53f80,
0xc000,0xbfb50000,0xc0000000,0x3fb54000,0x4000,0xbfb5c000,0x40000000,0xbfb50000,0xc000,0x3fb50000,0xc0000000,0xbfb5c000,
0x3e493f80,0x3fc63f80,0x3fffbf80,0x3fa2bf80,0xbf15bffb,0xbf713ec8,0xbff53ec8,0x3fe23ffb,0x3f713fed,0xbff5bfed,0x3fe2bf44,0xbf153f44,
0xbfa2bfd5,0x3e49bf8e,0xbfc63f8e,0xbfffbfd5,0x3ec83f80,0x3fd53f80,0x3ffb3f80,0x3f8e3f80,0xbf8ebfed,0xbec83f44,0xbfd53f44,0x3ffb3fed,
0x3fd53fb5,0xbffbbfb5,0x3f8ebfb5,0x3ec83fb5,0xbffbbf44,0xbf8ebfed,0xbec83fed,0xbfd5bf44,0x3f153f80,0x3fe23f80,0x3ff5bf80,0x3f71bf80,
0xbfc6bfd5,0x3e493f8e,0xbfa23f8e,0x3fff3fd5,0x3fff3f44,0xbfc6bf44,0x3e49bfed,0x3fa23fed,0xbfe23ec8,0xbff5bffb,0x3f713ffb,0xbf153ec8,
0x3f443f80,0x3fed3f80,0x3fed3f80,0x3f443f80,0xbfedbfb5,0x3f443fb5,0xbf443fb5,0x3fed3fb5,0x3fed0000,0xbf440000,0xbf44c000,0x3fed4000,
0xbf443fb5,0xbfedbfb5,0x3fed3fb5,0x3f443fb5,0x3f713f80,0x3ff53f80,0x3fe2bf80,0x3f15bf80,0xbfffbf8e,0x3fa23fd5,0xbe493fd5,0x3fc63f8e,
0x3fa2bf44,0x3e493f44,0xbfc6bfed,0x3fff3fed,0x3f153ffb,0xbf71bec8,0x3ff53ec8,0x3fe23ffb,0x3f8e3f80,0x3ffb3f80,0x3fd53f80,0x3ec83f80,
0xbffbbf44,0x3fd53fed,0x3ec83fed,0x3f8e3f44,0x3ec8bfb5,0x3f8e3fb5,0xbffbbfb5,0x3fd53fb5,0x3fd53fed,0x3ec83f44,0x3f8ebf44,0x3ffb3fed,
0x3fa23f80,0x3fff3f80,0x3fc6bf80,0x3e49bf80,0xbfe2bec8,0x3ff53ffb,0x3f713ffb,0x3f153ec8,0xbf15bfed,0x3fe23fed,0xbff5bf44,0x3f713f44,
0x3fff3f8e,0x3fc63fd5,0xbe49bfd5,0x3fa23f8e,0x40004000,0x3fb54000,0x0,0xbfb50000,0x40004000,0xbfb50000,0x0,0xbfb5c000,
0x40004000,0xbfb5c000,0x0,0x3fb50000,0x40004000,0x3fb50000,0x0,0x3fb54000,0x3fa23fb5,0xbe493fb5,0xbfc6bfb5,0xbfffbfb5,
0x3f713f8e,0xbff5bfd5,0xbfe2bfd5,0x3f15bf8e,0x3f153f44,0x3f71bf44,0xbff5bfed,0x3fe23fed,0x3e493ec8,0x3fc63ffb,0xbfffbffb,0xbfa23ec8,
0xbec80000,0xbfd50000,0xbffbc000,0xbf8ec000,0xbf8ebf44,0xbec8bfed,0xbfd5bfed,0x3ffb3f44,0xbfd5bfb5,0x3ffb3fb5,0xbf8ebfb5,0xbec83fb5,
0xbffbbfed,0xbf8e3f44,0xbec8bf44,0xbfd5bfed,0xbfe2bfb5,0xbff5bfb5,0xbf71bfb5,0x3f15bfb5,0xbfffbffb,0x3fc6bec8,0x3e49bec8,0x3fa23ffb,
0xbfc6bfed,0x3e493fed,0x3fa23f44,0xbfffbf44,0xbf15bf8e,0xbfe2bfd5,0x3ff53fd5,0x3f71bf8e,0xbfedc000,0xbf44c000,0x3f440000,0x3fed0000,
0xbf44bfb5,0x3fed3fb5,0x3fed3fb5,0xbf443fb5,0x3f440000,0xbfed0000,0x3fed4000,0xbf44c000,0x3fed3fb5,0x3f44bfb5,0x3f443fb5,0x3fed3fb5,
0xbf15bfb5,0x3f71bfb5,0x3ff53fb5,0x3fe23fb5,0x3fa23ec8,0x3e493ffb,0x3fc63ffb,0xbfffbec8,0x3fff3fed,0xbfa2bfed,0xbe493f44,0x3fc6bf44,
0x3f713fd5,0x3ff53f8e,0xbfe2bf8e,0xbf153fd5,0x3f8e0000,0x3ffb0000,0x3fd54000,0x3ec84000,0x3ffb3fed,0xbfd53f44,0xbec83f44,0xbf8ebfed,
0x3ec83fb5,0x3f8ebfb5,0xbffbbfb5,0x3fd53fb5,0xbfd5bf44,0xbec83fed,0xbf8ebfed,0xbffbbf44,0x3fff3fb5,0x3fc63fb5,0x3e493fb5,0xbfa23fb5,
0x3f153fd5,0xbfe2bf8e,0xbff5bf8e,0x3f71bfd5,0xbfe2bf44,0x3ff53f44,0xbf71bfed,0xbf153fed,0xbfa2bffb,0xbfffbec8,0x3fc63ec8,0x3e49bffb,
0x4000,0xbfb54000,0xc0000000,0xbfb50000,0xc000,0x3fb50000,0x40000000,0xbfb54000,0x4000,0x3fb5c000,0xc0000000,0x3fb50000,
0xc000,0xbfb50000,0x40000000,0x3fb5c000,0xbfc63fb5,0xbfff3fb5,0xbfa2bfb5,0x3e49bfb5,0x3fe2bf8e,0xbf153fd5,0x3f713fd5,0xbff53f8e,
0xbff53f44,0x3fe2bf44,0xbf15bfed,0xbf713fed,0x3fffbec8,0x3fa2bffb,0x3e493ffb,0x3fc6bec8,0xbffb0000,0xbf8e0000,0x3ec8c000,0x3fd5c000,
0x3fd53f44,0xbffb3fed,0xbf8e3fed,0xbec8bf44,0xbf8ebfb5,0xbec83fb5,0x3fd5bfb5,0xbffb3fb5,0x3ec83fed,0x3fd5bf44,0xbffb3f44,0xbf8e3fed,
0xbf71bfb5,0x3f15bfb5,0x3fe2bfb5,0x3ff5bfb5,0xbe493ffb,0xbfa23ec8,0xbfff3ec8,0x3fc6bffb,0x3fa2bfed,0xbfff3fed,0x3fc63f44,0xbe49bf44,
0xbff53f8e,0xbf713fd5,0xbf15bfd5,0xbfe23f8e,0x3f44c000,0x3fedc000,0x3fed0000,0x3f440000,0xbfed3fb5,0x3f44bfb5,0xbf44bfb5,0x3fedbfb5,
0x3fed0000,0xbf440000,0xbf444000,0x3fedc000,0xbf44bfb5,0xbfed3fb5,0x3fedbfb5,0x3f44bfb5,0x3ff5bfb5,0x3fe2bfb5,0x3f153fb5,0xbf713fb5,
0xbfc6bec8,0x3fffbffb,0x3fa2bffb,0x3e493ec8,0xbe493fed,0x3fc6bfed,0xbfff3f44,0x3fa2bf44,0x3fe2bfd5,0x3f15bf8e,0x3f713f8e,0x3ff5bfd5,
0x3fd50000,0x3ec80000,0xbf8e4000,0xbffb4000,0x3ec8bfed,0x3f8ebf44,0x3ffbbf44,0xbfd53fed,0xbffb3fb5,0x3fd5bfb5,0xbec8bfb5,0xbf8e3fb5,
0x3f8e3f44,0x3ffbbfed,0xbfd53fed,0xbec83f44,0x3e493fb5,0xbfa23fb5,0xbfff3fb5,0xbfc63fb5,0x3ff5bfd5,0xbf713f8e,0x3f153f8e,0xbfe23fd5,
0xbf71bf44,0xbf153f44,0x3fe2bfed,0xbff53fed,0xbfc63ffb,0xbe493ec8,0xbfa2bec8,0xbfff3ffb,0xc0004000,0xbfb54000,0x0,0x3fb50000,
0xc0004000,0x3fb50000,0x0,0x3fb5c000,0xc0004000,0x3fb5c000,0x0,0xbfb50000,0xc0004000,0xbfb50000,0x0,0xbfb54000,
0xbfa23fb5,0x3e493fb5,0x3fc6bfb5,0x3fffbfb5,0xbf713f8e,0x3ff5bfd5,0x3fe2bfd5,0xbf15bf8e,0xbf153f44,0xbf71bf44,0x3ff5bfed,0xbfe23fed,
0xbe493ec8,0xbfc63ffb,0x3fffbffb,0x3fa23ec8,0x3ec80000,0x3fd50000,0x3ffbc000,0x3f8ec000,0x3f8ebf44,0x3ec8bfed,0x3fd5bfed,0xbffb3f44,
0x3fd5bfb5,0xbffb3fb5,0x3f8ebfb5,0x3ec83fb5,0x3ffbbfed,0x3f8e3f44,0x3ec8bf44,0x3fd5bfed,0x3fe2bfb5,0x3ff5bfb5,0x3f71bfb5,0xbf15bfb5,
0x3fffbffb,0xbfc6bec8,0xbe49bec8,0xbfa23ffb,0x3fc6bfed,0xbe493fed,0xbfa23f44,0x3fffbf44,0x3f15bf8e,0x3fe2bfd5,0xbff53fd5,0xbf71bf8e,
0x3fedc000,0x3f44c000,0xbf440000,0xbfed0000,0x3f44bfb5,0xbfed3fb5,0xbfed3fb5,0x3f443fb5,0xbf440000,0x3fed0000,0xbfed4000,0x3f44c000,
0xbfed3fb5,0xbf44bfb5,0xbf443fb5,0xbfed3fb5,0x3f15bfb5,0xbf71bfb5,0xbff53fb5,0xbfe23fb5,0xbfa23ec8,0xbe493ffb,0xbfc63ffb,0x3fffbec8,
0xbfff3fed,0x3fa2bfed,0x3e493f44,0xbfc6bf44,0xbf713fd5,0xbff53f8e,0x3fe2bf8e,0x3f153fd5,0xbf8e0000,0xbffb0000,0xbfd54000,0xbec84000,
0xbffb3fed,0x3fd53f44,0x3ec83f44,0x3f8ebfed,0xbec83fb5,0xbf8ebfb5,0x3ffbbfb5,0xbfd53fb5,0x3fd5bf44,0x3ec83fed,0x3f8ebfed,0x3ffbbf44,
0xbfff3fb5,0xbfc63fb5,0xbe493fb5,0x3fa23fb5,0xbf153fd5,0x3fe2bf8e,0x3ff5bf8e,0xbf71bfd5,0x3fe2bf44,0xbff53f44,0x3f71bfed,0x3f153fed,
0x3fa2bffb,0x3fffbec8,0xbfc63ec8,0xbe49bffb,0x4000,0x3fb54000,0x40000000,0x3fb50000,0xc000,0xbfb50000,0xc0000000,0x3fb54000,
0x4000,0xbfb5c000,0x40000000,0xbfb50000,0xc000,0x3fb50000,0xc0000000,0xbfb5c000,0x3fc63fb5,0x3fff3fb5,0x3fa2bfb5,0xbe49bfb5,
0xbfe2bf8e,0x3f153fd5,0xbf713fd5,0x3ff53f8e,0x3ff53f44,0xbfe2bf44,0x3f15bfed,0x3f713fed,0xbfffbec8,0xbfa2bffb,0xbe493ffb,0xbfc6bec8,
0x3ffb0000,0x3f8e0000,0xbec8c000,0xbfd5c000,0xbfd53f44,0x3ffb3fed,0x3f8e3fed,0x3ec8bf44,0x3f8ebfb5,0x3ec83fb5,0xbfd5bfb5,0x3ffb3fb5,
0xbec83fed,0xbfd5bf44,0x3ffb3f44,0x3f8e3fed,0x3f71bfb5,0xbf15bfb5,0xbfe2bfb5,0xbff5bfb5,0x3e493ffb,0x3fa23ec8,0x3fff3ec8,0xbfc6bffb,
0xbfa2bfed,0x3fff3fed,0xbfc63f44,0x3e49bf44,0x3ff53f8e,0x3f713fd5,0x3f15bfd5,0x3fe23f8e,0xbf44c000,0xbfedc000,0xbfed0000,0xbf440000,
0x3fed3fb5,0xbf44bfb5,0x3f44bfb5,0xbfedbfb5,0xbfed0000,0x3f440000,0x3f444000,0xbfedc000,0x3f44bfb5,0x3fed3fb5,0xbfedbfb5,0xbf44bfb5,
0xbff5bfb5,0xbfe2bfb5,0xbf153fb5,0x3f713fb5,0x3fc6bec8,0xbfffbffb,0xbfa2bffb,0xbe493ec8,0x3e493fed,0xbfc6bfed,0x3fff3f44,0xbfa2bf44,
0xbfe2bfd5,0xbf15bf8e,0xbf713f8e,0xbff5bfd5,0xbfd50000,0xbec80000,0x3f8e4000,0x3ffb4000,0xbec8bfed,0xbf8ebf44,0xbffbbf44,0x3fd53fed,
0x3ffb3fb5,0xbfd5bfb5,0x3ec8bfb5,0x3f8e3fb5,0xbf8e3f44,0xbffbbfed,0x3fd53fed,0x3ec83f44,0xbe493fb5,0x3fa23fb5,0x3fff3fb5,0x3fc63fb5,
0xbff5bfd5,0x3f713f8e,0xbf153f8e,0x3fe23fd5,0x3f71bf44,0x3f153f44,0xbfe2bfed,0x3ff53fed,0x3fc63ffb,0x3e493ec8,0x3fa2bec8,0x3fff3ffb,
0x40004000,0x3fb54000,0x0,0xbfb50000,0x40004000,0xbfb50000,0x0,0xbfb5c000,0x40004000,0xbfb5c000,0x0,0x3fb50000,
0x40004000,0x3fb50000,0x0,0x3fb54000,0xbe490000,0xbfc60000,0xbfffc000,0xbfa2c000,0xbf15bec8,0xbf71bffb,0xbff5bffb,0x3fe23ec8,
0xbf71bf44,0x3ff53f44,0xbfe2bfed,0x3f153fed,0xbfa2bf8e,0x3e493fd5,0xbfc6bfd5,0xbfffbf8e,0xbffbc000,0xbf8ec000,0x3ec80000,0x3fd50000,
0xbfd5bfed,0x3ffb3f44,0x3f8e3f44,0x3ec83fed,0xbf8ebfb5,0xbec83fb5,0x3fd53fb5,0xbffbbfb5,0xbec8bf44,0xbfd5bfed,0x3ffb3fed,0x3f8ebf44,
0x3f150000,0x3fe20000,0x3ff54000,0x3f714000,0x3fc63f8e,0xbe493fd5,0x3fa23fd5,0xbfffbf8e,0x3fff3fed,0xbfc6bfed,0x3e493f44,0x3fa2bf44,
0x3fe23ffb,0x3ff53ec8,0xbf71bec8,0x3f153ffb,0x3fed4000,0x3f444000,0xbf440000,0xbfed0000,0x3f443fb5,0xbfedbfb5,0xbfedbfb5,0x3f44bfb5,
0xbf440000,0x3fed0000,0xbfedc000,0x3f444000,0xbfedbfb5,0xbf443fb5,0xbf44bfb5,0xbfedbfb5,0xbf710000,0xbff50000,0xbfe2c000,0xbf15c000,
0xbfffbfd5,0x3fa2bf8e,0xbe49bf8e,0x3fc63fd5,0xbfa2bfed,0xbe493fed,0x3fc63f44,0xbfffbf44,0x3f15bec8,0xbf71bffb,0x3ff53ffb,0x3fe2bec8,
0xbfd5c000,0xbec8c000,0x3f8e0000,0x3ffb0000,0x3ec8bf44,0x3f8e3fed,0x3ffb3fed,0xbfd53f44,0x3ffb3fb5,0xbfd5bfb5,0x3ec83fb5,0x3f8ebfb5,
0x3f8e3fed,0x3ffb3f44,0xbfd5bf44,0xbec83fed,0x3fa20000,0x3fff0000,0x3fc64000,0x3e494000,0x3fe23ffb,0xbff53ec8,0xbf713ec8,0xbf15bffb,
0xbf153f44,0x3fe2bf44,0xbff5bfed,0x3f713fed,0xbfffbfd5,0xbfc63f8e,0x3e49bf8e,0xbfa2bfd5,0x4000,0xbfb54000,0xc0000000,0xbfb50000,
0xc000,0x3fb50000,0x40000000,0xbfb54000,0x4000,0x3fb5c000,0xc0000000,0x3fb50000,0xc000,0xbfb50000,0x40000000,0x3fb5c000,
0xbfff0000,0xbfa20000,0x3e49c000,0x3fc6c000,0x3ff53ec8,0xbfe23ffb,0xbf153ffb,0xbf71bec8,0xbfe2bf44,0x3f153f44,0x3f71bfed,0xbff53fed,
0x3fc63f8e,0x3fffbfd5,0xbfa23fd5,0x3e493f8e,0x3ec8c000,0x3fd5c000,0x3ffb0000,0x3f8e0000,0xbf8e3fed,0xbec8bf44,0xbfd5bf44,0x3ffbbfed,
0x3fd5bfb5,0xbffb3fb5,0x3f8e3fb5,0x3ec8bfb5,0xbffb3f44,0xbf8e3fed,0xbec8bfed,0xbfd53f44,0x3ff50000,0x3f710000,0xbf154000,0xbfe24000,
0xbfa2bf8e,0x3fffbfd5,0x3fc6bfd5,0xbe493f8e,0x3e493fed,0x3fa2bfed,0xbfff3f44,0x3fc6bf44,0x3f71bffb,0xbf15bec8,0x3fe23ec8,0x3ff5bffb,
0xbf444000,0xbfed4000,0xbfed0000,0xbf440000,0x3fedbfb5,0xbf443fb5,0x3f443fb5,0xbfed3fb5,0xbfed0000,0x3f440000,0x3f44c000,0xbfed4000,
0x3f443fb5,0x3fedbfb5,0xbfed3fb5,0xbf443fb5,0xbfe20000,0xbf150000,0x3f71c000,0x3ff5c000,0x3e493fd5,0xbfc63f8e,0xbfff3f8e,0x3fa2bfd5,
0x3fc6bfed,0xbfff3fed,0x3fa23f44,0x3e49bf44,0xbff53ec8,0xbfe23ffb,0x3f15bffb,0xbf713ec8,0x3f8ec000,0x3ffbc000,0x3fd50000,0x3ec80000,
0xbffb3f44,0x3fd5bfed,0x3ec8bfed,0x3f8ebf44,0x3ec83fb5,0x3f8ebfb5,0xbffb3fb5,0x3fd5bfb5,0x3fd5bfed,0x3ec8bf44,0x3f8e3f44,0x3ffbbfed,
0x3fc60000,0x3e490000,0xbfa24000,0xbfff4000,0x3f71bffb,0x3f15bec8,0x3fe2bec8,0xbff53ffb,0xbff53f44,0x3f71bf44,0x3f15bfed,0xbfe23fed,
0xbe493fd5,0x3fa2bf8e,0xbfff3f8e,0xbfc63fd5,0xc0004000,0xbfb54000,0x0,0x3fb50000,0xc0004000,0x3fb50000,0x0,0x3fb5c000,
0xc0004000,0x3fb5c000,0x0,0xbfb50000,0xc0004000,0xbfb50000,0x0,0xbfb54000,0x3e490000,0x3fc60000,0x3fffc000,0x3fa2c000,
0x3f15bec8,0x3f71bffb,0x3ff5bffb,0xbfe23ec8,0x3f71bf44,0xbff53f44,0x3fe2bfed,0xbf153fed,0x3fa2bf8e,0xbe493fd5,0x3fc6bfd5,0x3fffbf8e,
0x3ffbc000,0x3f8ec000,0xbec80000,0xbfd50000,0x3fd5bfed,0xbffb3f44,0xbf8e3f44,0xbec83fed,0x3f8ebfb5,0x3ec83fb5,0xbfd53fb5,0x3ffbbfb5,
0x3ec8bf44,0x3fd5bfed,0xbffb3fed,0xbf8ebf44,0xbf150000,0xbfe20000,0xbff54000,0xbf714000,0xbfc63f8e,0x3e493fd5,0xbfa23fd5,0x3fffbf8e,
0xbfff3fed,0x3fc6bfed,0xbe493f44,0xbfa2bf44,0xbfe23ffb,0xbff53ec8,0x3f71bec8,0xbf153ffb,0xbfed4000,0xbf444000,0x3f440000,0x3fed0000,
0xbf443fb5,0x3fedbfb5,0x3fedbfb5,0xbf44bfb5,0x3f440000,0xbfed0000,0x3fedc000,0xbf444000,0x3fedbfb5,0x3f443fb5,0x3f44bfb5,0x3fedbfb5,
0x3f710000,0x3ff50000,0x3fe2c000,0x3f15c000,0x3fffbfd5,0xbfa2bf8e,0x3e49bf8e,0xbfc63fd5,0x3fa2bfed,0x3e493fed,0xbfc63f44,0x3fffbf44,
0xbf15bec8,0x3f71bffb,0xbff53ffb,0xbfe2bec8,0x3fd5c000,0x3ec8c000,0xbf8e0000,0xbffb0000,0xbec8bf44,0xbf8e3fed,0xbffb3fed,0x3fd53f44,
0xbffb3fb5,0x3fd5bfb5,0xbec83fb5,0xbf8ebfb5,0xbf8e3fed,0xbffb3f44,0x3fd5bf44,0x3ec83fed,0xbfa20000,0xbfff0000,0xbfc64000,0xbe494000,
0xbfe23ffb,0x3ff53ec8,0x3f713ec8,0x3f15bffb,0x3f153f44,0xbfe2bf44,0x3ff5bfed,0xbf713fed,0x3fffbfd5,0x3fc63f8e,0xbe49bf8e,0x3fa2bfd5,
0x4000,0x3fb54000,0x40000000,0x3fb50000,0xc000,0xbfb50000,0xc0000000,0x3fb54000,0x4000,0xbfb5c000,0x40000000,0xbfb50000,
0xc000,0x3fb50000,0xc0000000,0xbfb5c000,0x3fff0000,0x3fa20000,0xbe49c000,0xbfc6c000,0xbff53ec8,0x3fe23ffb,0x3f153ffb,0x3f71bec8,
0x3fe2bf44,0xbf153f44,0xbf71bfed,0x3ff53fed,0xbfc63f8e,0xbfffbfd5,0x3fa23fd5,0xbe493f8e,0xbec8c000,0xbfd5c000,0xbffb0000,0xbf8e0000,
0x3f8e3fed,0x3ec8bf44,0x3fd5bf44,0xbffbbfed,0xbfd5bfb5,0x3ffb3fb5,0xbf8e3fb5,0xbec8bfb5,0x3ffb3f44,0x3f8e3fed,0x3ec8bfed,0x3fd53f44,
0xbff50000,0xbf710000,0x3f154000,0x3fe24000,0x3fa2bf8e,0xbfffbfd5,0xbfc6bfd5,0x3e493f8e,0xbe493fed,0xbfa2bfed,0x3fff3f44,0xbfc6bf44,
0xbf71bffb,0x3f15bec8,0xbfe23ec8,0xbff5bffb,0x3f444000,0x3fed4000,0x3fed0000,0x3f440000,0xbfedbfb5,0x3f443fb5,0xbf443fb5,0x3fed3fb5,
0x3fed0000,0xbf440000,0xbf44c000,0x3fed4000,0xbf443fb5,0xbfedbfb5,0x3fed3fb5,0x3f443fb5,0x3fe20000,0x3f150000,0xbf71c000,0xbff5c000,
0xbe493fd5,0x3fc63f8e,0x3fff3f8e,0xbfa2bfd5,0xbfc6bfed,0x3fff3fed,0xbfa23f44,0xbe49bf44,0x3ff53ec8,0x3fe23ffb,0xbf15bffb,0x3f713ec8,
0xbf8ec000,0xbffbc000,0xbfd50000,0xbec80000,0x3ffb3f44,0xbfd5bfed,0xbec8bfed,0xbf8ebf44,0xbec83fb5,0xbf8ebfb5,0x3ffb3fb5,0xbfd5bfb5,
0xbfd5bfed,0xbec8bf44,0xbf8e3f44,0xbffbbfed,0xbfc60000,0xbe490000,0x3fa24000,0x3fff4000,0xbf71bffb,0xbf15bec8,0xbfe2bec8,0x3ff53ffb,
0x3ff53f44,0xbf71bf44,0xbf15bfed,0x3fe23fed,0x3e493fd5,0xbfa2bf8e,0x3fff3f8e,0x3fc63fd5,0x40004000,0x3fb54000,0x0,0xbfb50000,
0x40004000,0xbfb50000,0x0,0xbfb5c000,0x40004000,0xbfb5c000,0x0,0x3fb50000,0x40004000,0x3fb50000,0x0,0x3fb54000,
0xbfc6bfb5,0xbfffbfb5,0xbfa2bfb5,0x3e49bfb5,0xbfe2bfd5,0x3f15bf8e,0xbf71bf8e,0x3ff53fd5,0xbff5bfed,0x3fe23fed,0xbf15bf44,0xbf713f44,
0xbfffbffb,0xbfa23ec8,0xbe49bec8,0xbfc6bffb,0x3ec80000,0x3fd50000,0x3ffb4000,0x3f8e4000,0x3f8e3f44,0x3ec83fed,0x3fd53fed,0xbffbbf44,
0x3fd53fb5,0xbffbbfb5,0x3f8e3fb5,0x3ec8bfb5,0x3ffb3fed,0x3f8ebf44,0x3ec83f44,0x3fd53fed,0x3f713fb5,0xbf153fb5,0xbfe2bfb5,0xbff5bfb5,
0xbe493ec8,0xbfa2bffb,0xbfffbffb,0x3fc6bec8,0xbfa2bf44,0x3fff3f44,0xbfc6bfed,0x3e493fed,0xbff5bfd5,0xbf713f8e,0xbf15bf8e,0xbfe2bfd5,
0xbfedc000,0xbf44c000,0x3f440000,0x3fed0000,0xbf44bfb5,0x3fed3fb5,0x3fed3fb5,0xbf443fb5,0x3f440000,0xbfed0000,0x3fed4000,0xbf44c000,
0x3fed3fb5,0x3f44bfb5,0x3f443fb5,0x3fed3fb5,0x3ff53fb5,0x3fe23fb5,0x3f153fb5,0xbf713fb5,0x3fc63ffb,0xbfffbec8,0xbfa2bec8,0xbe49bffb,
0xbe493f44,0x3fc6bf44,0xbfffbfed,0x3fa23fed,0xbfe2bf8e,0xbf153fd5,0xbf71bfd5,0xbff5bf8e,0xbf8e0000,0xbffb0000,0xbfd5c000,0xbec8c000,
0xbffbbfed,0x3fd5bf44,0x3ec8bf44,0x3f8e3fed,0xbec8bfb5,0xbf8e3fb5,0x3ffb3fb5,0xbfd5bfb5,0x3fd53f44,0x3ec8bfed,0x3f8e3fed,0x3ffb3f44,
0xbe49bfb5,0x3fa2bfb5,0x3fff3fb5,0x3fc63fb5,0x3ff53f8e,0xbf713fd5,0x3f153fd5,0xbfe2bf8e,0x3f713fed,0x3f15bfed,0xbfe2bf44,0x3ff53f44,
0xbfc6bec8,0xbe493ffb,0xbfa2bffb,0xbfffbec8,0x4000,0xbfb54000,0xc0000000,0xbfb50000,0xc000,0x3fb50000,0x40000000,0xbfb54000,
0x4000,0x3fb5c000,0xc0000000,0x3fb50000,0xc000,0xbfb50000,0x40000000,0x3fb5c000,0xbfa2bfb5,0x3e49bfb5,0x3fc6bfb5,0x3fffbfb5,
0x3f713fd5,0xbff53f8e,0xbfe23f8e,0x3f15bfd5,0xbf15bfed,0xbf713fed,0x3ff5bf44,0xbfe23f44,0x3e493ffb,0x3fc6bec8,0xbfff3ec8,0xbfa23ffb,
0x3ffb0000,0x3f8e0000,0xbec84000,0xbfd54000,0xbfd5bf44,0x3ffbbfed,0x3f8ebfed,0x3ec83f44,0x3f8e3fb5,0x3ec8bfb5,0xbfd53fb5,0x3ffbbfb5,
0xbec8bfed,0xbfd53f44,0x3ffbbf44,0x3f8ebfed,0xbfe23fb5,0xbff53fb5,0xbf71bfb5,0x3f15bfb5,0x3fffbec8,0xbfc63ffb,0xbe493ffb,0xbfa23ec8,
0xbfc6bf44,0x3e493f44,0x3fa2bfed,0xbfff3fed,0x3f153fd5,0x3fe2bf8e,0xbff53f8e,0xbf713fd5,0x3f44c000,0x3fedc000,0x3fed0000,0x3f440000,
0xbfed3fb5,0x3f44bfb5,0xbf44bfb5,0x3fedbfb5,0x3fed0000,0xbf440000,0xbf444000,0x3fedc000,0xbf44bfb5,0xbfed3fb5,0x3fedbfb5,0x3f44bfb5,
0x3f153fb5,0xbf713fb5,0xbff53fb5,0xbfe23fb5,0x3fa2bffb,0x3e493ec8,0x3fc63ec8,0xbfff3ffb,0xbfff3f44,0x3fa2bf44,0x3e49bfed,0xbfc63fed,
0x3f713f8e,0x3ff5bfd5,0xbfe23fd5,0xbf153f8e,0xbfd50000,0xbec80000,0x3f8ec000,0x3ffbc000,0xbec83fed,0xbf8e3f44,0xbffb3f44,0x3fd5bfed,
0x3ffbbfb5,0xbfd53fb5,0x3ec83fb5,0x3f8ebfb5,0xbf8ebf44,0xbffb3fed,0x3fd5bfed,0x3ec8bf44,0x3fffbfb5,0x3fc6bfb5,0x3e493fb5,0xbfa23fb5,
0xbf15bf8e,0x3fe2bfd5,0x3ff5bfd5,0xbf713f8e,0xbfe23fed,0x3ff5bfed,0xbf71bf44,0xbf153f44,0x3fa23ec8,0x3fffbffb,0xbfc63ffb,0xbe493ec8,
0xc0004000,0xbfb54000,0x0,0x3fb50000,0xc0004000,0x3fb50000,0x0,0x3fb5c000,0xc0004000,0x3fb5c000,0x0,0xbfb50000,
0xc0004000,0xbfb50000,0x0,0xbfb54000,0x3fc6bfb5,0x3fffbfb5,0x3fa2bfb5,0xbe49bfb5,0x3fe2bfd5,0xbf15bf8e,0x3f71bf8e,0xbff53fd5,
0x3ff5bfed,0xbfe23fed,0x3f15bf44,0x3f713f44,0x3fffbffb,0x3fa23ec8,0x3e49bec8,0x3fc6bffb,0xbec80000,0xbfd50000,0xbffb4000,0xbf8e4000,
0xbf8e3f44,0xbec83fed,0xbfd53fed,0x3ffbbf44,0xbfd53fb5,0x3ffbbfb5,0xbf8e3fb5,0xbec8bfb5,0xbffb3fed,0xbf8ebf44,0xbec83f44,0xbfd53fed,
0xbf713fb5,0x3f153fb5,0x3fe2bfb5,0x3ff5bfb5,0x3e493ec8,0x3fa2bffb,0x3fffbffb,0xbfc6bec8,0x3fa2bf44,0xbfff3f44,0x3fc6bfed,0xbe493fed,
0x3ff5bfd5,0x3f713f8e,0x3f15bf8e,0x3fe2bfd5,0x3fedc000,0x3f44c000,0xbf440000,0xbfed0000,0x3f44bfb5,0xbfed3fb5,0xbfed3fb5,0x3f443fb5,
0xbf440000,0x3fed0000,0xbfed4000,0x3f44c000,0xbfed3fb5,0xbf44bfb5,0xbf443fb5,0xbfed3fb5,0xbff53fb5,0xbfe23fb5,0xbf153fb5,0x3f713fb5,
0xbfc63ffb,0x3fffbec8,0x3fa2bec8,0x3e49bffb,0x3e493f44,0xbfc6bf44,0x3fffbfed,0xbfa23fed,0x3fe2bf8e,0x3f153fd5,0x3f71bfd5,0x3ff5bf8e,
0x3f8e0000,0x3ffb0000,0x3fd5c000,0x3ec8c000,0x3ffbbfed,0xbfd5bf44,0xbec8bf44,0xbf8e3fed,0x3ec8bfb5,0x3f8e3fb5,0xbffb3fb5,0x3fd5bfb5,
0xbfd53f44,0xbec8bfed,0xbf8e3fed,0xbffb3f44,0x3e49bfb5,0xbfa2bfb5,0xbfff3fb5,0xbfc63fb5,0xbff53f8e,0x3f713fd5,0xbf153fd5,0x3fe2bf8e,
0xbf713fed,0xbf15bfed,0x3fe2bf44,0xbff53f44,0x3fc6bec8,0x3e493ffb,0x3fa2bffb,0x3fffbec8,0x4000,0x3fb54000,0x40000000,0x3fb50000,
0xc000,0xbfb50000,0xc0000000,0x3fb54000,0x4000,0xbfb5c000,0x40000000,0xbfb50000,0xc000,0x3fb50000,0xc0000000,0xbfb5c000,
0x3fa2bfb5,0xbe49bfb5,0xbfc6bfb5,0xbfffbfb5,0xbf713fd5,0x3ff53f8e,0x3fe23f8e,0xbf15bfd5,0x3f15bfed,0x3f713fed,0xbff5bf44,0x3fe23f44,
0xbe493ffb,0xbfc6bec8,0x3fff3ec8,0x3fa23ffb,0xbffb0000,0xbf8e0000,0x3ec84000,0x3fd54000,0x3fd5bf44,0xbffbbfed,0xbf8ebfed,0xbec83f44,
0xbf8e3fb5,0xbec8bfb5,0x3fd53fb5,0xbffbbfb5,0x3ec8bfed,0x3fd53f44,0xbffbbf44,0xbf8ebfed,0x3fe23fb5,0x3ff53fb5,0x3f71bfb5,0xbf15bfb5,
0xbfffbec8,0x3fc63ffb,0x3e493ffb,0x3fa23ec8,0x3fc6bf44,0xbe493f44,0xbfa2bfed,0x3fff3fed,0xbf153fd5,0xbfe2bf8e,0x3ff53f8e,0x3f713fd5,
0xbf44c000,0xbfedc000,0xbfed0000,0xbf440000,0x3fed3fb5,0xbf44bfb5,0x3f44bfb5,0xbfedbfb5,0xbfed0000,0x3f440000,0x3f444000,0xbfedc000,
0x3f44bfb5,0x3fed3fb5,0xbfedbfb5,0xbf44bfb5,0xbf153fb5,0x3f713fb5,0x3ff53fb5,0x3fe23fb5,0xbfa2bffb,0xbe493ec8,0xbfc63ec8,0x3fff3ffb,
0x3fff3f44,0xbfa2bf44,0xbe49bfed,0x3fc63fed,0xbf713f8e,0xbff5bfd5,0x3fe23fd5,0x3f153f8e,0x3fd50000,0x3ec80000,0xbf8ec000,0xbffbc000,
0x3ec83fed,0x3f8e3f44,0x3ffb3f44,0xbfd5bfed,0xbffbbfb5,0x3fd53fb5,0xbec83fb5,0xbf8ebfb5,0x3f8ebf44,0x3ffb3fed,0xbfd5bfed,0xbec8bf44,
0xbfffbfb5,0xbfc6bfb5,0xbe493fb5,0x3fa23fb5,0x3f15bf8e,0xbfe2bfd5,0xbff5bfd5,0x3f713f8e,0x3fe23fed,0xbff5bfed,0x3f71bf44,0x3f153f44,
0xbfa23ec8,0xbfffbffb,0x3fc63ffb,0x3e493ec8,0x80003f80,0x3f800000,0x80003f80,0x3f800000,0x80003f80,0x3f800000,0x80003f80,0x3f800000,
0x80003f80,0x3f800000,0x80003f80,0x3f800000,0x80003f80,0x3f800000,0x80003f80,0x3f800000,0x80003f80,0x3f800000,0x8000bf80,0xbf800000,
0x3f353f35,0x3f35bf35,0xbf35bf35,0xbf353f35,0x3f800000,0xbf80,0xbf800000,0x3f80,0x3f35bf35,0xbf35bf35,0xbf353f35,0x3f353f35,
0x80003f80,0x3f800000,0x80003f80,0x3f800000,0x3f800000,0xbf80,0x3f800000,0xbf80,0x8000bf80,0xbf800000,0x8000bf80,0xbf800000,
0xbf800000,0x3f80,0xbf800000,0x3f80,0x80003f80,0x3f800000,0x8000bf80,0xbf800000,0x3f35bf35,0xbf35bf35,0xbf353f35,0x3f353f35,
0xbf800000,0x3f80,0x3f800000,0xbf80,0x3f353f35,0x3f35bf35,0xbf35bf35,0xbf353f35,0x80003f80,0x3f800000,0x80003f80,0x3f800000,
0x8000bf80,0xbf800000,0x8000bf80,0xbf800000,0x80003f80,0x3f800000,0x80003f80,0x3f800000,0x8000bf80,0xbf800000,0x8000bf80,0xbf800000,
0x80003f80,0x3f800000,0x8000bf80,0xbf800000,0xbf35bf35,0xbf353f35,0x3f353f35,0x3f35bf35,0x3f800000,0xbf80,0xbf800000,0x3f80,
0xbf353f35,0x3f353f35,0x3f35bf35,0xbf35bf35,0x80003f80,0x3f800000,0x80003f80,0x3f800000,0xbf800000,0x3f80,0xbf800000,0x3f80,
0x8000bf80,0xbf800000,0x8000bf80,0xbf800000,0x3f800000,0xbf80,0x3f800000,0xbf80,0x80003f80,0x3f800000,0x8000bf80,0xbf800000,
0xbf353f35,0x3f353f35,0x3f35bf35,0xbf35bf35,0xbf800000,0x3f80,0x3f800000,0xbf80,0xbf35bf35,0xbf353f35,0x3f353f35,0x3f35bf35,
0x3f803f80,0x80008000,0x80008000,0xbf80bf80,0x3f803f80,0x80008000,0x80008000,0xbf80bf80,0x3f803f80,0x80008000,0x80008000,0xbf80bf80,
0x3f803f80,0x80008000,0x80008000,0xbf80bf80,0x3f353f80,0x3f358000,0x3f358000,0xbf35bf80,0xbf350000,0x3f353f80,0x3f353f80,0x3f358000,
0xbf35bf80,0xbf358000,0xbf358000,0x3f353f80,0x3f350000,0xbf35bf80,0xbf35bf80,0xbf358000,0x3f80,0x3f808000,0x3f808000,0x8000bf80,
0xbf80,0xbf808000,0xbf808000,0x80003f80,0x3f80,0x3f808000,0x3f808000,0x8000bf80,0xbf80,0xbf808000,0xbf808000,0x80003f80,
0xbf353f80,0x3f358000,0x3f358000,0x3f35bf80,0x3f350000,0x3f35bf80,0x3f35bf80,0xbf358000,0x3f35bf80,0xbf358000,0xbf358000,0xbf353f80,
0xbf350000,0xbf353f80,0xbf353f80,0x3f358000,0xbf803f80,0x80008000,0x80008000,0x3f80bf80,0xbf803f80,0x80008000,0x80008000,0x3f80bf80,
0xbf803f80,0x80008000,0x80008000,0x3f80bf80,0xbf803f80,0x80008000,0x80008000,0x3f80bf80,0xbf353f80,0xbf358000,0xbf358000,0x3f35bf80,
0x3f350000,0xbf353f80,0xbf353f80,0xbf358000,0x3f35bf80,0x3f358000,0x3f358000,0xbf353f80,0xbf350000,0x3f35bf80,0x3f35bf80,0x3f358000,
0x3f80,0xbf808000,0xbf808000,0x8000bf80,0xbf80,0x3f808000,0x3f808000,0x80003f80,0x3f80,0xbf808000,0xbf808000,0x8000bf80,
0xbf80,0x3f808000,0x3f808000,0x80003f80,0x3f353f80,0xbf358000,0xbf358000,0xbf35bf80,0xbf350000,0xbf35bf80,0xbf35bf80,0x3f358000,
0xbf35bf80,0x3f358000,0x3f358000,0x3f353f80,0x3f350000,0x3f353f80,0x3f353f80,0xbf358000,0x3f800000,0x0,0x3f800000,0x0,
0x3f800000,0x0,0x3f800000,0x0,0x3f800000,0x0,0x3f800000,0x0,0x3f800000,0x0,0x3f800000,0x0,
0x3f800000,0x0,0x3f7fb10f,0xbd48fb30,0x3f7ec46d,0xbdc8bd36,0x3f7d3aac,0xbe164083,0x3f7b14be,0xbe47c5c2,0x3f7853f8,0xbe78cfcc,
0x3f74fa0b,0xbe94a031,0x3f710908,0xbeac7cd4,0x3f800000,0x0,0x3f7ec46d,0xbdc8bd36,0x3f7b14be,0xbe47c5c2,0x3f74fa0b,0xbe94a031,
0x3f6c835e,0xbec3ef15,0x3f61c598,0xbef15aea,0x3f54db31,0xbf0e39da,0x3f45e403,0xbf226799,0x3f800000,0x0,0x3f7d3aac,0xbe164083,
0x3f74fa0b,0xbe94a031,0x3f676bd8,0xbedae880,0x3f54db31,0xbf0e39da,0x3f3daef9,0xbf2beb4a,0x3f226799,0xbf45e403,0x3f039c3d,0xbf5b941a,
0x3f800000,0x0,0x3f7b14be,0xbe47c5c2,0x3f6c835e,0xbec3ef15,0x3f54db31,0xbf0e39da,0x3f3504f3,0xbf3504f3,0x3f0e39da,0xbf54db31,
0x3ec3ef15,0xbf6c835e,0x3e47c5c2,0xbf7b14be,0x3f800000,0x0,0x3f7853f8,0xbe78cfcc,0x3f61c598,0xbef15aea,0x3f3daef9,0xbf2beb4a,
0x3f0e39da,0xbf54db31,0x3eac7cd4,0xbf710908,0x3dc8bd36,0xbf7ec46d,0xbe164083,0xbf7d3aac,0x3f800000,0x0,0x3f74fa0b,0xbe94a031,
0x3f54db31,0xbf0e39da,0x3f226799,0xbf45e403,0x3ec3ef15,0xbf6c835e,0x3dc8bd36,0xbf7ec46d,0xbe47c5c2,0xbf7b14be,0xbef15aea,0xbf61c598,
0x3f800000,0x0,0x3f710908,0xbeac7cd4,0x3f45e403,0xbf226799,0x3f039c3d,0xbf5b941a,0x3e47c5c2,0xbf7b14be,0xbe164083,0xbf7d3aac,
0xbef15aea,0xbf61c598,0xbf3daef9,0xbf2beb4a,0x3f800000,0x0,0x3f800000,0x0,0x3f800000,0x0,0x3f800000,0x0,
0x3f800000,0x0,0x3f800000,0x0,0x3f800000,0x0,0x3f800000,0x0,0x3f6c835e,0xbec3ef15,0x3f676bd8,0xbedae880,
0x3f61c598,0xbef15aea,0x3f5b941a,0xbf039c3d,0x3f54db31,0xbf0e39da,0x3f4d9f02,0xbf187fc0,0x3f45e403,0xbf226799,0x3f3daef9,0xbf2beb4a,
0x3f3504f3,0xbf3504f3,0x3f226799,0xbf45e403,0x3f0e39da,0xbf54db31,0x3ef15aea,0xbf61c598,0x3ec3ef15,0xbf6c835e,0x3e94a031,0xbf74fa0b,
0x3e47c5c2,0xbf7b14be,0x3dc8bd36,0xbf7ec46d,0x3ec3ef15,0xbf6c835e,0x3e78cfcc,0xbf7853f8,0x3dc8bd36,0xbf7ec46d,0xbd48fb30,0xbf7fb10f,
0xbe47c5c2,0xbf7b14be,0xbeac7cd4,0xbf710908,0xbef15aea,0xbf61c598,0xbf187fc0,0xbf4d9f02,0x0,0xbf800000,0xbe47c5c2,0xbf7b14be,
0xbec3ef15,0xbf6c835e,0xbf0e39da,0xbf54db31,0xbf3504f3,0xbf3504f3,0xbf54db31,0xbf0e39da,0xbf6c835e,0xbec3ef15,0xbf7b14be,0xbe47c5c2,
0xbec3ef15,0xbf6c835e,0xbf187fc0,0xbf4d9f02,0xbf45e403,0xbf226799,0xbf676bd8,0xbedae880,0xbf7b14be,0xbe47c5c2,0xbf7fb10f,0x3d48fb30,
0xbf74fa0b,0x3e94a031,0xbf5b941a,0x3f039c3d,0xbf3504f3,0xbf3504f3,0xbf61c598,0xbef15aea,0xbf7b14be,0xbe47c5c2,0xbf7ec46d,0x3dc8bd36,
0xbf6c835e,0x3ec3ef15,0xbf45e403,0x3f226799,0xbf0e39da,0x3f54db31,0xbe94a031,0x3f74fa0b,0xbf6c835e,0xbec3ef15,0xbf7fb10f,0xbd48fb30,
0xbf74fa0b,0x3e94a031,0xbf4d9f02,0x3f187fc0,0xbf0e39da,0x3f54db31,0xbe78cfcc,0x3f7853f8,0x3dc8bd36,0x3f7ec46d,0x3edae880,0x3f676bd8,
0x80003f80,0x3f800000,0x3f800000,0xbf80,0x3ec43f6d,0x3f6dbec4,0x3f6dbec4,0xbec4bf6d,0x3f353f35,0x3f35bf35,0x3f35bf35,0xbf35bf35,
0x3f6d3ec4,0x3ec4bf6d,0x3ec4bf6d,0xbf6dbec4,0x80003f80,0x3f800000,0xbf800000,0x3f80,0x3f6d3ec4,0x3ec4bf6d,0xbec43f6d,0x3f6d3ec4,
0x3f35bf35,0xbf35bf35,0x3f353f35,0x3f35bf35,0xbec4bf6d,0xbf6d3ec4,0x3f6dbec4,0xbec4bf6d,0x80003f80,0x3f800000,0x3f800000,0xbf80,
0x3f6dbec4,0xbec4bf6d,0xbec4bf6d,0xbf6d3ec4,0xbf35bf35,0xbf353f35,0xbf353f35,0x3f353f35,0xbec43f6d,0x3f6d3ec4,0x3f6d3ec4,0x3ec4bf6d,
0x80003f80,0x3f800000,0xbf800000,0x3f80,0x3ec4bf6d,0xbf6dbec4,0x3f6d3ec4,0x3ec4bf6d,0xbf353f35,0x3f353f35,0xbf35bf35,0xbf353f35,
0x3f6dbec4,0xbec4bf6d,0x3ec43f6d,0x3f6dbec4,0x80003f80,0x3f800000,0x3f800000,0xbf80,0xbec4bf6d,0xbf6d3ec4,0xbf6d3ec4,0x3ec43f6d,
0x3f353f35,0x3f35bf35,0x3f35bf35,0xbf35bf35,0xbf6dbec4,0xbec43f6d,0xbec43f6d,0x3f6d3ec4,0x80003f80,0x3f800000,0xbf800000,0x3f80,
0xbf6dbec4,0xbec43f6d,0x3ec4bf6d,0xbf6dbec4,0x3f35bf35,0xbf35bf35,0x3f353f35,0x3f35bf35,0x3ec43f6d,0x3f6dbec4,0xbf6d3ec4,0x3ec43f6d,
0x80003f80,0x3f800000,0x3f800000,0xbf80,0xbf6d3ec4,0x3ec43f6d,0x3ec43f6d,0x3f6dbec4,0xbf35bf35,0xbf353f35,0xbf353f35,0x3f353f35,
0x3ec4bf6d,0xbf6dbec4,0xbf6dbec4,0xbec43f6d,0x80003f80,0x3f800000,0xbf800000,0x3f80,0xbec43f6d,0x3f6d3ec4,0xbf6dbec4,0xbec43f6d,
0xbf353f35,0x3f353f35,0xbf35bf35,0xbf353f35,0xbf6d3ec4,0x3ec43f6d,0xbec4bf6d,0xbf6d3ec4,0x3f803f80,0x80008000,0x80008000,0xbf80bf80,
0x3f803f80,0x80008000,0x80008000,0xbf80bf80,0x3f803f80,0x80008000,0x80008000,0xbf80bf80,0x3f803f80,0x80008000,0x80008000,0xbf80bf80,
0x3ec43f6d,0x3f6d3ec4,0x3f6d3ec4,0xbec4bf6d,0xbf6dbec4,0x3ec43f6d,0x3ec43f6d,0x3f6d3ec4,0xbec4bf6d,0xbf6dbec4,0xbf6dbec4,0x3ec43f6d,
0x3f6d3ec4,0xbec4bf6d,0xbec4bf6d,0xbf6dbec4,0xbf353f35,0x3f353f35,0x3f353f35,0x3f35bf35,0x3f35bf35,0xbf35bf35,0xbf35bf35,0xbf353f35,
0xbf353f35,0x3f353f35,0x3f353f35,0x3f35bf35,0x3f35bf35,0xbf35bf35,0xbf35bf35,0xbf353f35,0xbf6d3ec4,0xbec43f6d,0xbec43f6d,0x3f6dbec4,
0xbec43f6d,0x3f6dbec4,0x3f6dbec4,0x3ec4bf6d,0x3f6dbec4,0x3ec4bf6d,0x3ec4bf6d,0xbf6d3ec4,0x3ec4bf6d,0xbf6d3ec4,0xbf6d3ec4,0xbec43f6d,
0x0,0xbf803f80,0xbf803f80,0x80008000,0x0,0xbf803f80,0xbf803f80,0x80008000,0x0,0xbf803f80,0xbf803f80,0x80008000,
0x0,0xbf803f80,0xbf803f80,0x80008000,0x3f6dbec4,0xbec43f6d,0xbec43f6d,0xbf6d3ec4,0x3ec4bf6d,0x3f6dbec4,0x3f6dbec4,0xbec43f6d,
0xbf6d3ec4,0x3ec4bf6d,0x3ec4bf6d,0x3f6dbec4,0xbec43f6d,0xbf6d3ec4,0xbf6d3ec4,0x3ec4bf6d,0x3f35bf35,0x3f353f35,0x3f353f35,0xbf353f35,
0xbf353f35,0xbf35bf35,0xbf35bf35,0x3f35bf35,0x3f35bf35,0x3f353f35,0x3f353f35,0xbf353f35,0xbf353f35,0xbf35bf35,0xbf35bf35,0x3f35bf35,
0xbec4bf6d,0x3f6d3ec4,0x3f6d3ec4,0x3ec43f6d,0x3f6d3ec4,0x3ec43f6d,0x3ec43f6d,0xbf6dbec4,0x3ec43f6d,0xbf6dbec4,0xbf6dbec4,0xbec4bf6d,
0xbf6dbec4,0xbec4bf6d,0xbec4bf6d,0x3f6d3ec4,0x3f800000,0x0,0x3f7fec43,0xbcc90ab0,0x3f7fb10f,0xbd48fb30,0x3f7f4e6d,0xbd96a905,
0x3f7ec46d,0xbdc8bd36,0x3f7e1324,0xbdfab273,0x3f7d3aac,0xbe164083,0x3f7c3b28,0xbe2f10a2,0x3f800000,0x0,0x3f7f4e6d,0xbd96a905,
0x3f7d3aac,0xbe164083,0x3f79c79d,0xbe605c13,0x3f74fa0b,0xbe94a031,0x3f6ed89e,0xbeb8442a,0x3f676bd8,0xbedae880,0x3f5ebe05,0xbefc5d27,
0x3f800000,0x0,0x3f7e1324,0xbdfab273,0x3f7853f8,0xbe78cfcc,0x3f6ed89e,0xbeb8442a,0x3f61c598,0xbef15aea,0x3f514d3d,0xbf13682a,
0x3f3daef9,0xbf2beb4a,0x3f273656,0xbf41d870,0x3f800000,0x0,0x3f7c3b28,0xbe2f10a2,0x3f710908,0xbeac7cd4,0x3f5ebe05,0xbefc5d27,
0x3f45e403,0xbf226799,0x3f273656,0xbf41d870,0x3f039c3d,0xbf5b941a,0x3eb8442a,0xbf6ed89e,0x3f800000,0x0,0x3f79c79d,0xbe605c13,
0x3f676bd8,0xbedae880,0x3f49d112,0xbf1d7fd1,0x3f226799,0xbf45e403,0x3ee63375,0xbf64aa59,0x3e78cfcc,0xbf7853f8,0x3cc90ab0,0xbf7fec43,
0x3f800000,0x0,0x3f76ba07,0xbe888e93,0x3f5b941a,0xbf039c3d,0x3f3085bb,0xbf396842,0x3ef15aea,0xbf61c598,0x3e605c13,0xbf79c79d,
0xbd48fb30,0xbf7fb10f,0xbea09ae5,0xbf731447,0x3f800000,0x0,0x3f731447,0xbea09ae5,0x3f4d9f02,0xbf187fc0,0x3f13682a,0xbf514d3d,
0x3e94a031,0xbf74fa0b,0xbcc90ab0,0xbf7fec43,0xbeac7cd4,0xbf710908,0xbf1d7fd1,0xbf49d112,0x3f800000,0x0,0x3f6ed89e,0xbeb8442a,
0x3f3daef9,0xbf2beb4a,0x3ee63375,0xbf64aa59,0x3dc8bd36,0xbf7ec46d,0xbe888e93,0xbf76ba07,0xbf187fc0,0xbf4d9f02,0xbf584853,0xbf08f59b,
0x3f7b14be,0xbe47c5c2,0x3f79c79d,0xbe605c13,0x3f7853f8,0xbe78cfcc,0x3f76ba07,0xbe888e93,0x3f74fa0b,0xbe94a031,0x3f731447,0xbea09ae5,
0x3f710908,0xbeac7cd4,0x3f6ed89e,0xbeb8442a,0x3f54db31,0xbf0e39da,0x3f49d112,0xbf1d7fd1,0x3f3daef9,0xbf2beb4a,0x3f3085bb,0xbf396842,
0x3f226799,0xbf45e403,0x3f13682a,0xbf514d3d,0x3f039c3d,0xbf5b941a,0x3ee63375,0xbf64aa59,0x3f0e39da,0xbf54db31,0x3ee63375,0xbf64aa59,
0x3eac7cd4,0xbf710908,0x3e605c13,0xbf79c79d,0x3dc8bd36,0xbf7ec46d,0xbcc90ab0,0xbf7fec43,0xbe164083,0xbf7d3aac,0xbe888e93,0xbf76ba07,
0x3e47c5c2,0xbf7b14be,0x3cc90ab0,0xbf7fec43,0xbe164083,0xbf7d3aac,0xbea09ae5,0xbf731447,0xbef15aea,0xbf61c598,0xbf1d7fd1,0xbf49d112,
0xbf3daef9,0xbf2beb4a,0xbf584853,0xbf08f59b,0xbe47c5c2,0xbf7b14be,0xbecf7bca,0xbf6a09a7,0xbf187fc0,0xbf4d9f02,0xbf41d870,0xbf273656,
0xbf61c598,0xbef15aea,0xbf76ba07,0xbe888e93,0xbf7fb10f,0xbd48fb30,0xbf7c3b28,0x3e2f10a2,0xbf0e39da,0xbf54db31,0xbf41d870,0xbf273656,
0xbf676bd8,0xbedae880,0xbf7c3b28,0xbe2f10a2,0xbf7ec46d,0x3dc8bd36,0xbf6ed89e,0x3eb8442a,0xbf4d9f02,0x3f187fc0,0xbf1d7fd1,0x3f49d112,
0xbf54db31,0xbf0e39da,0xbf76ba07,0xbe888e93,0xbf7fb10f,0x3d48fb30,0xbf6ed89e,0x3eb8442a,0xbf45e403,0x3f226799,0xbf08f59b,0x3f584853,
0xbe78cfcc,0x3f7853f8,0x3d96a905,0x3f7f4e6d,0xbf7b14be,0xbe47c5c2,0xbf7c3b28,0x3e2f10a2,0xbf5b941a,0x3f039c3d,0xbf1d7fd1,0x3f49d112,
0xbe94a031,0x3f74fa0b,0x3d96a905,0x3f7f4e6d,0x3edae880,0x3f676bd8,0x3f396842,0x3f3085bb,0x80003f80,0x80003f80,0x80003f80,0x80003f80,
0x80003f80,0x80003f80,0x80003f80,0x80003f80,0x80003f80,0x80003f80,0x80003f80,0x80003f80,0x80003f80,0x80003f80,0x80003f80,0x80003f80,
0x3f800000,0x3f800000,0x3f800000,0x3f800000,0x3f800000,0x3f800000,0x3f800000,0x3f800000,0x3f800000,0x3f800000,0x3f800000,0x3f800000,
0x3f800000,0x3f800000,0x3f800000,0x3f800000,0x80003f80,0x3f353f35,0x80003f80,0x3f353f35,0x3f800000,0x3f35bf35,0x3f800000,0x3f35bf35,
0x8000bf80,0xbf35bf35,0x8000bf80,0xbf35bf35,0xbf800000,0xbf353f35,0xbf800000,0xbf353f35,0x3f800000,0x3f35bf35,0x3f800000,0x3f35bf35,
0xbf80,0xbf35bf35,0xbf80,0xbf35bf35,0xbf800000,0xbf353f35,0xbf800000,0xbf353f35,0x3f80,0x3f353f35,0x3f80,0x3f353f35,
0x80003f80,0x3f800000,0x80003f80,0x3f800000,0x8000bf80,0xbf800000,0x8000bf80,0xbf800000,0x80003f80,0x3f800000,0x80003f80,0x3f800000,
0x8000bf80,0xbf800000,0x8000bf80,0xbf800000,0x3f800000,0xbf80,0x3f800000,0xbf80,0xbf800000,0x3f80,0xbf800000,0x3f80,
0x3f800000,0xbf80,0x3f800000,0xbf80,0xbf800000,0x3f80,0xbf800000,0x3f80,0x80003f80,0x3f35bf35,0x80003f80,0x3f35bf35,
0xbf800000,0x3f353f35,0xbf800000,0x3f353f35,0x8000bf80,0xbf353f35,0x8000bf80,0xbf353f35,0x3f800000,0xbf35bf35,0x3f800000,0xbf35bf35,
0x3f800000,0xbf35bf35,0x3f800000,0xbf35bf35,0x3f80,0x3f35bf35,0x3f80,0x3f35bf35,0xbf800000,0x3f353f35,0xbf800000,0x3f353f35,
0xbf80,0xbf353f35,0xbf80,0xbf353f35,0x80003f80,0x3ec43f6d,0x8000bf80,0xbec4bf6d,0x3f353f35,0x3f6d3ec4,0xbf35bf35,0xbf6dbec4,
0x3f800000,0x3f6dbec4,0xbf800000,0xbf6d3ec4,0x3f35bf35,0x3ec4bf6d,0xbf353f35,0xbec43f6d,0x3f800000,0x3f6dbec4,0xbf800000,0xbf6d3ec4,
0x3f35bf35,0x3ec4bf6d,0xbf353f35,0xbec43f6d,0xbf80,0xbec4bf6d,0x3f80,0x3ec43f6d,0xbf35bf35,0xbf6dbec4,0x3f353f35,0x3f6d3ec4,
0x80003f80,0x3f6d3ec4,0x8000bf80,0xbf6dbec4,0x3f35bf35,0xbec4bf6d,0xbf353f35,0x3ec43f6d,0xbf800000,0xbec43f6d,0x3f800000,0x3ec4bf6d,
0x3f353f35,0x3f6dbec4,0xbf35bf35,0xbf6d3ec4,0x3f800000,0x3ec4bf6d,0xbf800000,0xbec43f6d,0xbf35bf35,0xbf6d3ec4,0x3f353f35,0x3f6dbec4,
0x3f80,0x3f6d3ec4,0xbf80,0xbf6dbec4,0x3f35bf35,0xbec4bf6d,0xbf353f35,0x3ec43f6d,0x80003f80,0x3f6dbec4,0x8000bf80,0xbf6d3ec4,
0xbf35bf35,0xbec43f6d,0x3f353f35,0x3ec4bf6d,0x3f800000,0xbec4bf6d,0xbf800000,0x3ec43f6d,0xbf353f35,0x3f6d3ec4,0x3f35bf35,0xbf6dbec4,
0x3f800000,0xbec4bf6d,0xbf800000,0x3ec43f6d,0xbf353f35,0x3f6d3ec4,0x3f35bf35,0xbf6dbec4,0xbf80,0xbf6d3ec4,0x3f80,0x3f6dbec4,
0x3f353f35,0x3ec4bf6d,0xbf35bf35,0xbec43f6d,0x80003f80,0x3ec4bf6d,0x8000bf80,0xbec43f6d,0xbf353f35,0x3f6dbec4,0x3f35bf35,0xbf6d3ec4,
0xbf800000,0x3f6d3ec4,0x3f800000,0xbf6dbec4,0xbf35bf35,0x3ec43f6d,0x3f353f35,0xbec4bf6d,0x3f800000,0xbf6dbec4,0xbf800000,0x3f6d3ec4,
0x3f353f35,0xbec4bf6d,0xbf35bf35,0x3ec43f6d,0x3f80,0x3ec4bf6d,0xbf80,0xbec43f6d,0xbf353f35,0x3f6dbec4,0x3f35bf35,0xbf6d3ec4,
0x80003f80,0x8000bf80,0x80003f80,0x8000bf80,0x80003f80,0x8000bf80,0x80003f80,0x8000bf80,0x80003f80,0x8000bf80,0x80003f80,0x8000bf80,
0x80003f80,0x8000bf80,0x80003f80,0x8000bf80,0x3f800000,0xbf800000,0x3f800000,0xbf800000,0x3f800000,0xbf800000,0x3f800000,0xbf800000,
0x3f800000,0xbf800000,0x3f800000,0xbf800000,0x3f800000,0xbf800000,0x3f800000,0xbf800000,0x80003f80,0xbf35bf35,0x80003f80,0xbf35bf35,
0x3f800000,0xbf353f35,0x3f800000,0xbf353f35,0x8000bf80,0x3f353f35,0x8000bf80,0x3f353f35,0xbf800000,0x3f35bf35,0xbf800000,0x3f35bf35,
0x3f800000,0xbf353f35,0x3f800000,0xbf353f35,0xbf80,0x3f353f35,0xbf80,0x3f353f35,0xbf800000,0x3f35bf35,0xbf800000,0x3f35bf35,
0x3f80,0xbf35bf35,0x3f80,0xbf35bf35,0x80003f80,0xbf800000,0x80003f80,0xbf800000,0x8000bf80,0x3f800000,0x8000bf80,0x3f800000,
0x80003f80,0xbf800000,0x80003f80,0xbf800000,0x8000bf80,0x3f800000,0x8000bf80,0x3f800000,0x3f800000,0x3f80,0x3f800000,0x3f80,
0xbf800000,0xbf80,0xbf800000,0xbf80,0x3f800000,0x3f80,0x3f800000,0x3f80,0xbf800000,0xbf80,0xbf800000,0xbf80,
0x80003f80,0xbf353f35,0x80003f80,0xbf353f35,0xbf800000,0xbf35bf35,0xbf800000,0xbf35bf35,0x8000bf80,0x3f35bf35,0x8000bf80,0x3f35bf35,
0x3f800000,0x3f353f35,0x3f800000,0x3f353f35,0x3f800000,0x3f353f35,0x3f800000,0x3f353f35,0x3f80,0xbf353f35,0x3f80,0xbf353f35,
0xbf800000,0xbf35bf35,0xbf800000,0xbf35bf35,0xbf80,0x3f35bf35,0xbf80,0x3f35bf35,0x80003f80,0xbec4bf6d,0x8000bf80,0x3ec43f6d,
0x3f353f35,0xbf6dbec4,0xbf35bf35,0x3f6d3ec4,0x3f800000,0xbf6d3ec4,0xbf800000,0x3f6dbec4,0x3f35bf35,0xbec43f6d,0xbf353f35,0x3ec4bf6d,
0x3f800000,0xbf6d3ec4,0xbf800000,0x3f6dbec4,0x3f35bf35,0xbec43f6d,0xbf353f35,0x3ec4bf6d,0xbf80,0x3ec43f6d,0x3f80,0xbec4bf6d,
0xbf35bf35,0x3f6d3ec4,0x3f353f35,0xbf6dbec4,0x80003f80,0xbf6dbec4,0x8000bf80,0x3f6d3ec4,0x3f35bf35,0x3ec43f6d,0xbf353f35,0xbec4bf6d,
0xbf800000,0x3ec4bf6d,0x3f800000,0xbec43f6d,0x3f353f35,0xbf6d3ec4,0xbf35bf35,0x3f6dbec4,0x3f800000,0xbec43f6d,0xbf800000,0x3ec4bf6d,
0xbf35bf35,0x3f6dbec4,0x3f353f35,0xbf6d3ec4,0x3f80,0xbf6dbec4,0xbf80,0x3f6d3ec4,0x3f35bf35,0x3ec43f6d,0xbf353f35,0xbec4bf6d,
0x80003f80,0xbf6d3ec4,0x8000bf80,0x3f6dbec4,0xbf35bf35,0x3ec4bf6d,0x3f353f35,0xbec43f6d,0x3f800000,0x3ec43f6d,0xbf800000,0xbec4bf6d,
0xbf353f35,0xbf6dbec4,0x3f35bf35,0x3f6d3ec4,0x3f800000,0x3ec43f6d,0xbf800000,0xbec4bf6d,0xbf353f35,0xbf6dbec4,0x3f35bf35,0x3f6d3ec4,
0xbf80,0x3f6dbec4,0x3f80,0xbf6d3ec4,0x3f353f35,0xbec43f6d,0xbf35bf35,0x3ec4bf6d,0x80003f80,0xbec43f6d,0x8000bf80,0x3ec4bf6d,
0xbf353f35,0xbf6d3ec4,0x3f35bf35,0x3f6dbec4,0xbf800000,0xbf6dbec4,0x3f800000,0x3f6d3ec4,0xbf35bf35,0xbec4bf6d,0x3f353f35,0x3ec43f6d,
0x3f800000,0x3f6d3ec4,0xbf800000,0xbf6dbec4,0x3f353f35,0x3ec43f6d,0xbf35bf35,0xbec4bf6d,0x3f80,0xbec43f6d,0xbf80,0x3ec4bf6d,
0xbf353f35,0xbf6d3ec4,0x3f35bf35,0x3f6dbec4,
};
constexpr int TB_F = 0, TB_E = 512, TB_P2 = 1024;

enum { C_EP = 0, C_Z1 = 32, C_Z2 = 96, C_H3 = 128, C_U = 160, C_X = 288, C_TOTAL = 512 };
struct Scratch {
  unsigned cnt[C_TOTAL];
  uint32_t moda[8 * 2 * D_];
  uint32_t mod[4 * D_ + 256];
  uint32_t z1[120 * 5120];
  uint32_t z2[128 * 4800];
  uint8_t h3[32 * 18 * 4096];
  uint8_t u[72 * D_ * 128];
};
__device__ __align__(1024) Scratch g_s;

#define PF2 8
#define PF2K 16
#define HOLDA 5
#define GOAT 0
#define H3W 0
#define X1K 10
#define PEEK 1
#define H3G 1
#define PFF 2
#ifndef NV1
#define NV1 12
#endif
#ifndef NV2
#define NV2 20
#endif
#define GDEP 0
#define TRK0 50
#define W0N 3
#define TRKC 350
#define J2 6
#define MODPOS 2
#define W2H 1
#define NG1 2

#define FAILCNT(k) do {} while (0)
#define CK(k) do {} while (0)
#define CKX(k) do {} while (0)
#define TS(k) do {} while (0)
#define TSC(k) do {} while (0)
struct Maps { CUtensorMap z1, z2[2], w1a, w1b, h3[2], w2, wf[4], wm; };
struct Params {
  const __nv_bfloat16 *x, *c, *wmod;
  Scratch* s;
  const uint4* tab;
  const __nv_bfloat16 *wr, *wi, *w1, *w2, *b1, *b2;
  uint32_t* out;
};

__device__ __forceinline__ uint32_t smem_u32(const void* p) { return (uint32_t)__cvta_generic_to_shared(p); }
__device__ __forceinline__ void mbar_init(uint32_t b, int c) { asm volatile("mbarrier.init.shared::cta.b64 [%0], %1;" ::"r"(b), "r"(c)); }
__device__ __forceinline__ void mbar_expect(uint32_t b, int bytes) { asm volatile("mbarrier.arrive.expect_tx.shared::cta.b64 _, [%0], %1;" ::"r"(b), "r"(bytes) : "memory"); }
__device__ __forceinline__ void mbar_arrive(uint32_t b) { asm volatile("mbarrier.arrive.shared::cta.b64 _, [%0];" ::"r"(b) : "memory"); }
#define MBAR_WAIT(SEM)                                                                                                         \
  asm volatile("{\n.reg .pred p;\n.reg .u32 it;\nmov.u32 it, 0;\nW:\nmbarrier.try_wait.parity" SEM ".shared::cta.b64 p, [%0], %1;\n" \
               "@p bra.uni D;\nadd.u32 it, it, 1;\nsetp.lt.u32 p, it, 0x400000;\n@p bra.uni W;\ntrap;\nD:\n}" ::"r"(b), "r"(ph) : "memory")
__device__ __forceinline__ void mbar_wait(uint32_t b, int ph) { MBAR_WAIT(""); }
__device__ __forceinline__ uint32_t mbar_test(uint32_t b, int ph) {
  uint32_t ok;
  asm volatile("{\n.reg .pred p;\nmbarrier.test_wait.parity.shared::cta.b64 p, [%1], %2;\nselp.u32 %0, 1, 0, p;\n}\n" : "=r"(ok) : "r"(b), "r"(ph) : "memory");
  return ok;
}
__device__ __forceinline__ void tma2d(uint32_t dst, const CUtensorMap* m, int c0, int c1, uint32_t bar) {
  asm volatile("cp.async.bulk.tensor.2d.shared::cluster.global.mbarrier::complete_tx::bytes [%0], [%1, {%3, %4}], [%2];" ::"r"(dst), "l"(m), "r"(bar), "r"(c0), "r"(c1) : "memory");
}
__device__ __forceinline__ uint64_t pol_ef() { uint64_t p; asm("createpolicy.fractional.L2::evict_first.b64 %0, 1.0;" : "=l"(p)); return p; }
__device__ __forceinline__ void tma3d_ef(uint32_t dst, const CUtensorMap* m, int c1, int c2, uint32_t bar) {
  asm volatile("cp.async.bulk.tensor.3d.shared::cluster.global.mbarrier::complete_tx::bytes.L2::cache_hint [%0], [%1, {%3, %4, %5}], [%2], %6;" ::"r"(dst), "l"(m), "r"(bar), "r"(0), "r"(c1), "r"(c2), "l"(pol_ef()) : "memory");
}
__device__ __forceinline__ void tma4d_ef(uint32_t dst, const CUtensorMap* m, int c1, int c2, int c3, uint32_t bar) {
  asm volatile("cp.async.bulk.tensor.4d.shared::cluster.global.mbarrier::complete_tx::bytes.L2::cache_hint [%0], [%1, {%3, %7, %4, %5}], [%2], %6;" ::"r"(dst), "l"(m), "r"(bar), "r"(0), "r"(c2), "r"(c3), "l"(pol_ef()), "r"(c1) : "memory");
}
__device__ __forceinline__ void bulk_ld(uint32_t dst, const void* src, int bytes, uint32_t bar) {
  asm volatile("cp.async.bulk.shared::cluster.global.mbarrier::complete_tx::bytes [%0], [%1], %2, [%3];" ::"r"(dst), "l"(src), "r"(bytes), "r"(bar) : "memory");
}
__device__ __forceinline__ void bulk_st(void* dst, uint32_t src, int bytes) {
  asm volatile("cp.async.bulk.global.shared::cta.bulk_group [%0], [%1], %2;" ::"l"(dst), "r"(src), "r"(bytes) : "memory");
}
__device__ __forceinline__ void tma_st2d(const CUtensorMap* m, uint32_t src, int c0, int c1) {
  asm volatile("cp.async.bulk.tensor.2d.global.shared::cta.bulk_group [%0, {%2, %3}], [%1];" ::"l"(m), "r"(src), "r"(c0), "r"(c1) : "memory");
}
__device__ __forceinline__ void tma_st3d(const CUtensorMap* m, uint32_t src, int c0, int c1, int c2) {
  asm volatile("cp.async.bulk.tensor.3d.global.shared::cta.bulk_group [%0, {%2, %3, %4}], [%1];" ::"l"(m), "r"(src), "r"(c0), "r"(c1), "r"(c2) : "memory");
}
__device__ __forceinline__ void bulk_commit_wait_read() {
  asm volatile("cp.async.bulk.commit_group;" ::: "memory");
  asm volatile("cp.async.bulk.wait_group.read 0;" ::: "memory");
}
__device__ __forceinline__ void bulk_commit_wait() {
  asm volatile("cp.async.bulk.commit_group;" ::: "memory");
  asm volatile("cp.async.bulk.wait_group 0;" ::: "memory");
}
__device__ __forceinline__ void prefetch_l2(const void* p, int bytes) {
  asm volatile("cp.async.bulk.prefetch.L2.global [%0], %1;" ::"l"(p), "r"(bytes) : "memory");
}
__device__ __forceinline__ void wg_fence() { asm volatile("wgmma.fence.sync.aligned;" ::: "memory"); }
__device__ __forceinline__ void wg_commit() { asm volatile("wgmma.commit_group.sync.aligned;" ::: "memory"); }
template <int N> __device__ __forceinline__ void wg_wait() { asm volatile("wgmma.wait_group.sync.aligned %0;" ::"n"(N) : "memory"); }
template <int N> __device__ __forceinline__ void reg_fence(float (&d)[N]) {
#pragma unroll
  for (int i = 0; i < N; i++) asm volatile("" : "+f"(d[i])::"memory");
}
__device__ __forceinline__ void fence_async_smem() { asm volatile("fence.proxy.async.shared::cta;" ::: "memory"); }
__device__ __forceinline__ void fence_async_glb() { asm volatile("fence.proxy.async.global;" ::: "memory"); }
__device__ __forceinline__ uint32_t ld_rlx(const void* p) { uint32_t v; asm volatile("ld.relaxed.gpu.global.b32 %0, [%1];" : "=r"(v) : "l"(p) : "memory"); return v; }
__device__ __forceinline__ uint2 ld_rlx2(const void* p) { uint2 v; asm volatile("ld.relaxed.gpu.global.v2.b32 {%0,%1}, [%2];" : "=r"(v.x), "=r"(v.y) : "l"(p) : "memory"); return v; }
__device__ __forceinline__ uint4 ld_rlx4(const void* p) { uint4 v; asm volatile("ld.relaxed.gpu.global.v4.b32 {%0,%1,%2,%3}, [%4];" : "=r"(v.x), "=r"(v.y), "=r"(v.z), "=r"(v.w) : "l"(p) : "memory"); return v; }
__device__ __forceinline__ uint32_t ld_nc(const void* p) { uint32_t v; asm volatile("ld.global.nc.L1::no_allocate.b32 %0, [%1];" : "=r"(v) : "l"(p) : "memory"); return v; }
__device__ __forceinline__ uint4 ld_nc4(const void* p) { uint4 v; asm volatile("ld.global.nc.v4.b32 {%0,%1,%2,%3}, [%4];" : "=r"(v.x), "=r"(v.y), "=r"(v.z), "=r"(v.w) : "l"(p) : "memory"); return v; }
__device__ __forceinline__ uint32_t lds(uint32_t a) { uint32_t v; asm volatile("ld.shared.b32 %0, [%1];" : "=r"(v) : "r"(a) : "memory"); return v; }
__device__ __forceinline__ uint2 lds2(uint32_t a) { uint2 v; asm volatile("ld.shared.v2.b32 {%0,%1}, [%2];" : "=r"(v.x), "=r"(v.y) : "r"(a) : "memory"); return v; }
__device__ __forceinline__ uint4 lds4(uint32_t a) { uint4 v; asm volatile("ld.shared.v4.b32 {%0,%1,%2,%3}, [%4];" : "=r"(v.x), "=r"(v.y), "=r"(v.z), "=r"(v.w) : "r"(a) : "memory"); return v; }
__device__ __forceinline__ float lds_bf(uint32_t a) { uint32_t v; asm volatile("ld.shared.u16 %0, [%1];" : "=r"(v) : "r"(a) : "memory"); return __uint_as_float(v << 16); }
__device__ __forceinline__ void sts(uint32_t a, uint32_t v) { asm volatile("st.shared.b32 [%0], %1;" ::"r"(a), "r"(v) : "memory"); }
__device__ __forceinline__ void sts2(uint32_t a, uint32_t v0, uint32_t v1) { asm volatile("st.shared.v2.b32 [%0], {%1,%2};" ::"r"(a), "r"(v0), "r"(v1) : "memory"); }
__device__ __forceinline__ void sts4(uint32_t a, uint32_t v0, uint32_t v1, uint32_t v2, uint32_t v3) { asm volatile("st.shared.v4.b32 [%0], {%1,%2,%3,%4};" ::"r"(a), "r"(v0), "r"(v1), "r"(v2), "r"(v3) : "memory"); }
__device__ __forceinline__ void bar_sync(int id, int n) { asm volatile("bar.sync %0, %1;" ::"r"(id), "r"(n) : "memory"); }
__device__ __forceinline__ void bar_arrive(int id, int n) { asm volatile("bar.arrive %0, %1;" ::"r"(id), "r"(n) : "memory"); }
__device__ __forceinline__ void red_add(unsigned* p, unsigned v) { asm volatile("red.relaxed.gpu.global.add.u32 [%0], %1;" ::"l"(p), "r"(v) : "memory"); }
__device__ __forceinline__ bool any(bool p) { return __any_sync(0xffffffffu, p); }
__device__ __forceinline__ void pause(unsigned clks) {
  asm volatile("{\n.reg .pred p;\n.reg .u32 a, b;\nmov.u32 a, %%clock;\nW:\nmov.u32 b, %%clock;\nsub.u32 b, b, a;\nsetp.lt.s32 p, b, %0;\n@p bra.uni W;\n}" ::"r"(clks) : "memory");
}
__device__ __forceinline__ void red_bf16x8(uint32_t* p, uint32_t a, uint32_t b, uint32_t c, uint32_t d) {
  asm volatile("red.relaxed.gpu.global.add.noftz.v4.bf16x2 [%0], {%1,%2,%3,%4};" ::"l"(p), "r"(a), "r"(b), "r"(c), "r"(d) : "memory");
}
__device__ __forceinline__ void red_bf16x4(uint32_t* p, uint32_t a, uint32_t b) {
  asm volatile("red.relaxed.gpu.global.add.noftz.v2.bf16x2 [%0], {%1,%2};" ::"l"(p), "r"(a), "r"(b) : "memory");
}
constexpr int SPIN_MAX = 1 << 20;
__device__ __forceinline__ uint32_t ld_acq(const void* p) { uint32_t v; asm volatile("ld.acquire.gpu.global.b32 %0, [%1];" : "=r"(v) : "l"(p) : "memory"); return v; }
template <bool ACQ = false> __device__ __forceinline__ void wait_cnt(const unsigned* p, unsigned target) {
  int it = 0;
  while (any((int)((ACQ ? ld_acq(p) : ld_rlx(p)) - target) < 0) && ++it < SPIN_MAX) {}
}
__device__ __forceinline__ uint32_t pack_bf16(float lo, float hi) { uint32_t r; asm("cvt.rn.bf16x2.f32 %0, %1, %2;" : "=r"(r) : "f"(hi), "f"(lo)); return r; }
__device__ __forceinline__ float bf_lo(uint32_t v) { return __uint_as_float(v << 16); }
__device__ __forceinline__ float bf_hi(uint32_t v) { return __uint_as_float(v & 0xffff0000u); }
__device__ __forceinline__ uint32_t hadd2(uint32_t a, uint32_t b) { uint32_t r; asm("add.rn.bf16x2 %0, %1, %2;" : "=r"(r) : "r"(a), "r"(b)); return r; }
__device__ __forceinline__ uint32_t hmul2(uint32_t a, uint32_t b) { uint32_t r; asm("mul.rn.bf16x2 %0, %1, %2;" : "=r"(r) : "r"(a), "r"(b)); return r; }
__device__ __forceinline__ uint32_t hfma2(uint32_t a, uint32_t b, uint32_t c) { uint32_t r; asm("fma.rn.bf16x2 %0, %1, %2, %3;" : "=r"(r) : "r"(a), "r"(b), "r"(c)); return r; }
__device__ __forceinline__ float rbf(float x) { uint32_t r; asm("cvt.rn.bf16x2.f32 %0, %1, %2;" : "=r"(r) : "f"(x), "f"(0.0f)); return __uint_as_float(r); }
__device__ __forceinline__ void stmatrix4(uint32_t a, uint32_t r0, uint32_t r1, uint32_t r2, uint32_t r3) {
  asm volatile("stmatrix.sync.aligned.m8n8.x4.shared.b16 [%0], {%1,%2,%3,%4};" ::"r"(a), "r"(r0), "r"(r1), "r"(r2), "r"(r3) : "memory");
}
__device__ __forceinline__ void stmatrix2(uint32_t a, uint32_t r0, uint32_t r1) {
  asm volatile("stmatrix.sync.aligned.m8n8.x2.shared.b16 [%0], {%1,%2};" ::"r"(a), "r"(r0), "r"(r1) : "memory");
}
__device__ __forceinline__ void stmatrix4t(uint32_t a, uint32_t r0, uint32_t r1, uint32_t r2, uint32_t r3) {
  asm volatile("stmatrix.sync.aligned.m8n8.x4.trans.shared.b16 [%0], {%1,%2,%3,%4};" ::"r"(a), "r"(r0), "r"(r1), "r"(r2), "r"(r3) : "memory");
}
__device__ __forceinline__ uint32_t movm(uint32_t a) { uint32_t r; asm("movmatrix.sync.aligned.m8n8.trans.b16 %0, %1;" : "=r"(r) : "r"(a)); return r; }
template <bool ACC> __device__ __forceinline__ void mma16(float* d, uint32_t a0, uint32_t a1, uint32_t a2, uint32_t a3, uint32_t b0, uint32_t b1) {
  if (ACC) asm("mma.sync.aligned.m16n8k16.row.col.f32.bf16.bf16.f32 {%0,%1,%2,%3}, {%4,%5,%6,%7}, {%8,%9}, {%0,%1,%2,%3};"
               : "+f"(d[0]), "+f"(d[1]), "+f"(d[2]), "+f"(d[3]) : "r"(a0), "r"(a1), "r"(a2), "r"(a3), "r"(b0), "r"(b1));
  else asm("mma.sync.aligned.m16n8k16.row.col.f32.bf16.bf16.f32 {%0,%1,%2,%3}, {%4,%5,%6,%7}, {%8,%9}, {%10,%10,%10,%10};"
           : "=f"(d[0]), "=f"(d[1]), "=f"(d[2]), "=f"(d[3]) : "r"(a0), "r"(a1), "r"(a2), "r"(a3), "r"(b0), "r"(b1), "f"(0.f));
}
__device__ __forceinline__ uint32_t pin(uint32_t v) { uint32_t r; asm volatile("shfl.sync.bfly.b32 %0, %1, 0, 31, 0xffffffff;" : "=r"(r) : "r"(v)); return r; }
template <class T> __device__ __forceinline__ T* pin(T* p) {
  const uint64_t a = reinterpret_cast<uint64_t>(p);
  return reinterpret_cast<T*>((uint64_t)pin((uint32_t)a) | ((uint64_t)pin((uint32_t)(a >> 32)) << 32));
}
__device__ __forceinline__ uint32_t upin(uint32_t v) { return __shfl_sync(0xffffffffu, v, 0); }
template <class T> __device__ __forceinline__ T* upin(T* p) {
  const uint64_t a = reinterpret_cast<uint64_t>(p);
  return reinterpret_cast<T*>((uint64_t)upin((uint32_t)a) | ((uint64_t)upin((uint32_t)(a >> 32)) << 32));
}
__device__ __forceinline__ bool elect() {
  uint32_t p;
  asm volatile("{\n.reg .pred P;\nelect.sync _|P, 0xffffffff;\nselp.u32 %0, 1, 0, P;\n}" : "=r"(p));
  return p;
}
__device__ __forceinline__ uint32_t set_tag(uint32_t w, uint32_t tag) { uint32_t r; asm("lop3.b32 %0, %1, 0xfffffffe, %2, 0xea;" : "=r"(r) : "r"(w), "r"(tag)); return r; }
__device__ __forceinline__ uint32_t bitsel(uint32_t w, uint32_t m, uint32_t o) { uint32_t r; asm("lop3.b32 %0, %1, %2, %3, 0xe2;" : "=r"(r) : "r"(w), "r"(m), "r"(o)); return r; }
__device__ __forceinline__ uint32_t or3(uint32_t a, uint32_t b, uint32_t c) { uint32_t r; asm("lop3.b32 %0, %1, %2, %3, 0xfe;" : "=r"(r) : "r"(a), "r"(b), "r"(c)); return r; }
__device__ __forceinline__ uint32_t diff2(uint32_t a, uint32_t b, uint32_t tag) { uint32_t r; asm("lop3.b32 %0, %1, %2, %3, 0x7e;" : "=r"(r) : "r"(a), "r"(b), "r"(tag)); return r; }
__device__ __forceinline__ float2 cmul(float2 a, float2 b) { return make_float2(a.x * b.x - a.y * b.y, a.x * b.y + a.y * b.x); }

template<int TB> __device__ __forceinline__ void wgmma_ss_160_0(float (&d)[96], uint32_t al, uint32_t ah, uint32_t bl, uint32_t bh) {
  asm volatile("{\n.reg .b64 da, db;\nmov.b64 da, {%80, %81};\nmov.b64 db, {%82, %83};\n"
    "wgmma.mma_async.sync.aligned.m64n160k16.f32.bf16.bf16 {%0,%1,%2,%3,%4,%5,%6,%7,%8,%9,%10,%11,%12,%13,%14,%15,%16,%17,%18,%19,%20,%21,%22,%23,%24,%25,%26,%27,%28,%29,%30,%31,%32,%33,%34,%35,%36,%37,%38,%39,%40,%41,%42,%43,%44,%45,%46,%47,%48,%49,%50,%51,%52,%53,%54,%55,%56,%57,%58,%59,%60,%61,%62,%63,%64,%65,%66,%67,%68,%69,%70,%71,%72,%73,%74,%75,%76,%77,%78,%79}, da, db, 1, 1, 1, 1, %84;\n}\n"
    : "+f"(d[0]),"+f"(d[1]),"+f"(d[2]),"+f"(d[3]),"+f"(d[4]),"+f"(d[5]),"+f"(d[6]),"+f"(d[7]),"+f"(d[8]),"+f"(d[9]),"+f"(d[10]),"+f"(d[11]),"+f"(d[12]),"+f"(d[13]),"+f"(d[14]),"+f"(d[15]),"+f"(d[16]),"+f"(d[17]),"+f"(d[18]),"+f"(d[19]),"+f"(d[20]),"+f"(d[21]),"+f"(d[22]),"+f"(d[23]),"+f"(d[24]),"+f"(d[25]),"+f"(d[26]),"+f"(d[27]),"+f"(d[28]),"+f"(d[29]),"+f"(d[30]),"+f"(d[31]),"+f"(d[32]),"+f"(d[33]),"+f"(d[34]),"+f"(d[35]),"+f"(d[36]),"+f"(d[37]),"+f"(d[38]),"+f"(d[39]),"+f"(d[40]),"+f"(d[41]),"+f"(d[42]),"+f"(d[43]),"+f"(d[44]),"+f"(d[45]),"+f"(d[46]),"+f"(d[47]),"+f"(d[48]),"+f"(d[49]),"+f"(d[50]),"+f"(d[51]),"+f"(d[52]),"+f"(d[53]),"+f"(d[54]),"+f"(d[55]),"+f"(d[56]),"+f"(d[57]),"+f"(d[58]),"+f"(d[59]),"+f"(d[60]),"+f"(d[61]),"+f"(d[62]),"+f"(d[63]),"+f"(d[64]),"+f"(d[65]),"+f"(d[66]),"+f"(d[67]),"+f"(d[68]),"+f"(d[69]),"+f"(d[70]),"+f"(d[71]),"+f"(d[72]),"+f"(d[73]),"+f"(d[74]),"+f"(d[75]),"+f"(d[76]),"+f"(d[77]),"+f"(d[78]),"+f"(d[79])
    : "r"(al), "r"(ah), "r"(bl), "r"(bh), "n"(TB));
}
template<int TB> __device__ __forceinline__ void wgmma_ss_144_0(float (&d)[96], uint32_t al, uint32_t ah, uint32_t bl, uint32_t bh) {
  asm volatile("{\n.reg .b64 da, db;\nmov.b64 da, {%72, %73};\nmov.b64 db, {%74, %75};\n"
    "wgmma.mma_async.sync.aligned.m64n144k16.f32.bf16.bf16 {%0,%1,%2,%3,%4,%5,%6,%7,%8,%9,%10,%11,%12,%13,%14,%15,%16,%17,%18,%19,%20,%21,%22,%23,%24,%25,%26,%27,%28,%29,%30,%31,%32,%33,%34,%35,%36,%37,%38,%39,%40,%41,%42,%43,%44,%45,%46,%47,%48,%49,%50,%51,%52,%53,%54,%55,%56,%57,%58,%59,%60,%61,%62,%63,%64,%65,%66,%67,%68,%69,%70,%71}, da, db, 1, 1, 1, 1, %76;\n}\n"
    : "+f"(d[0]),"+f"(d[1]),"+f"(d[2]),"+f"(d[3]),"+f"(d[4]),"+f"(d[5]),"+f"(d[6]),"+f"(d[7]),"+f"(d[8]),"+f"(d[9]),"+f"(d[10]),"+f"(d[11]),"+f"(d[12]),"+f"(d[13]),"+f"(d[14]),"+f"(d[15]),"+f"(d[16]),"+f"(d[17]),"+f"(d[18]),"+f"(d[19]),"+f"(d[20]),"+f"(d[21]),"+f"(d[22]),"+f"(d[23]),"+f"(d[24]),"+f"(d[25]),"+f"(d[26]),"+f"(d[27]),"+f"(d[28]),"+f"(d[29]),"+f"(d[30]),"+f"(d[31]),"+f"(d[32]),"+f"(d[33]),"+f"(d[34]),"+f"(d[35]),"+f"(d[36]),"+f"(d[37]),"+f"(d[38]),"+f"(d[39]),"+f"(d[40]),"+f"(d[41]),"+f"(d[42]),"+f"(d[43]),"+f"(d[44]),"+f"(d[45]),"+f"(d[46]),"+f"(d[47]),"+f"(d[48]),"+f"(d[49]),"+f"(d[50]),"+f"(d[51]),"+f"(d[52]),"+f"(d[53]),"+f"(d[54]),"+f"(d[55]),"+f"(d[56]),"+f"(d[57]),"+f"(d[58]),"+f"(d[59]),"+f"(d[60]),"+f"(d[61]),"+f"(d[62]),"+f"(d[63]),"+f"(d[64]),"+f"(d[65]),"+f"(d[66]),"+f"(d[67]),"+f"(d[68]),"+f"(d[69]),"+f"(d[70]),"+f"(d[71])
    : "r"(al), "r"(ah), "r"(bl), "r"(bh), "n"(TB));
}
template<int TB> __device__ __forceinline__ void wgmma_ss_96_0(float (&d)[96], uint32_t al, uint32_t ah, uint32_t bl, uint32_t bh) {
  asm volatile("{\n.reg .b64 da, db;\nmov.b64 da, {%48, %49};\nmov.b64 db, {%50, %51};\n"
    "wgmma.mma_async.sync.aligned.m64n96k16.f32.bf16.bf16 {%0,%1,%2,%3,%4,%5,%6,%7,%8,%9,%10,%11,%12,%13,%14,%15,%16,%17,%18,%19,%20,%21,%22,%23,%24,%25,%26,%27,%28,%29,%30,%31,%32,%33,%34,%35,%36,%37,%38,%39,%40,%41,%42,%43,%44,%45,%46,%47}, da, db, 1, 1, 1, 1, %52;\n}\n"
    : "+f"(d[0]),"+f"(d[1]),"+f"(d[2]),"+f"(d[3]),"+f"(d[4]),"+f"(d[5]),"+f"(d[6]),"+f"(d[7]),"+f"(d[8]),"+f"(d[9]),"+f"(d[10]),"+f"(d[11]),"+f"(d[12]),"+f"(d[13]),"+f"(d[14]),"+f"(d[15]),"+f"(d[16]),"+f"(d[17]),"+f"(d[18]),"+f"(d[19]),"+f"(d[20]),"+f"(d[21]),"+f"(d[22]),"+f"(d[23]),"+f"(d[24]),"+f"(d[25]),"+f"(d[26]),"+f"(d[27]),"+f"(d[28]),"+f"(d[29]),"+f"(d[30]),"+f"(d[31]),"+f"(d[32]),"+f"(d[33]),"+f"(d[34]),"+f"(d[35]),"+f"(d[36]),"+f"(d[37]),"+f"(d[38]),"+f"(d[39]),"+f"(d[40]),"+f"(d[41]),"+f"(d[42]),"+f"(d[43]),"+f"(d[44]),"+f"(d[45]),"+f"(d[46]),"+f"(d[47])
    : "r"(al), "r"(ah), "r"(bl), "r"(bh), "n"(TB));
}
template<int TB> __device__ __forceinline__ void wgmma_ss_96_48(float (&d)[96], uint32_t al, uint32_t ah, uint32_t bl, uint32_t bh) {
  asm volatile("{\n.reg .b64 da, db;\nmov.b64 da, {%48, %49};\nmov.b64 db, {%50, %51};\n"
    "wgmma.mma_async.sync.aligned.m64n96k16.f32.bf16.bf16 {%0,%1,%2,%3,%4,%5,%6,%7,%8,%9,%10,%11,%12,%13,%14,%15,%16,%17,%18,%19,%20,%21,%22,%23,%24,%25,%26,%27,%28,%29,%30,%31,%32,%33,%34,%35,%36,%37,%38,%39,%40,%41,%42,%43,%44,%45,%46,%47}, da, db, 1, 1, 1, 1, %52;\n}\n"
    : "+f"(d[48]),"+f"(d[49]),"+f"(d[50]),"+f"(d[51]),"+f"(d[52]),"+f"(d[53]),"+f"(d[54]),"+f"(d[55]),"+f"(d[56]),"+f"(d[57]),"+f"(d[58]),"+f"(d[59]),"+f"(d[60]),"+f"(d[61]),"+f"(d[62]),"+f"(d[63]),"+f"(d[64]),"+f"(d[65]),"+f"(d[66]),"+f"(d[67]),"+f"(d[68]),"+f"(d[69]),"+f"(d[70]),"+f"(d[71]),"+f"(d[72]),"+f"(d[73]),"+f"(d[74]),"+f"(d[75]),"+f"(d[76]),"+f"(d[77]),"+f"(d[78]),"+f"(d[79]),"+f"(d[80]),"+f"(d[81]),"+f"(d[82]),"+f"(d[83]),"+f"(d[84]),"+f"(d[85]),"+f"(d[86]),"+f"(d[87]),"+f"(d[88]),"+f"(d[89]),"+f"(d[90]),"+f"(d[91]),"+f"(d[92]),"+f"(d[93]),"+f"(d[94]),"+f"(d[95])
    : "r"(al), "r"(ah), "r"(bl), "r"(bh), "n"(TB));
}
__device__ __forceinline__ void wgmma_rs_72(float (&d)[36], uint32_t a0, uint32_t a1, uint32_t a2, uint32_t a3, uint32_t bl, uint32_t bh, int sd) {
  asm volatile("{\n.reg .pred p;\n.reg .b64 db;\nsetp.ne.b32 p, %42, 0;\nmov.b64 db, {%40, %41};\n"
    "wgmma.mma_async.sync.aligned.m64n72k16.f32.bf16.bf16 {%0,%1,%2,%3,%4,%5,%6,%7,%8,%9,%10,%11,%12,%13,%14,%15,%16,%17,%18,%19,%20,%21,%22,%23,%24,%25,%26,%27,%28,%29,%30,%31,%32,%33,%34,%35}, {%36,%37,%38,%39}, db, p, 1, 1, 1;\n}\n"
    : "+f"(d[0]),"+f"(d[1]),"+f"(d[2]),"+f"(d[3]),"+f"(d[4]),"+f"(d[5]),"+f"(d[6]),"+f"(d[7]),"+f"(d[8]),"+f"(d[9]),"+f"(d[10]),"+f"(d[11]),"+f"(d[12]),"+f"(d[13]),"+f"(d[14]),"+f"(d[15]),"+f"(d[16]),"+f"(d[17]),"+f"(d[18]),"+f"(d[19]),"+f"(d[20]),"+f"(d[21]),"+f"(d[22]),"+f"(d[23]),"+f"(d[24]),"+f"(d[25]),"+f"(d[26]),"+f"(d[27]),"+f"(d[28]),"+f"(d[29]),"+f"(d[30]),"+f"(d[31]),"+f"(d[32]),"+f"(d[33]),"+f"(d[34]),"+f"(d[35])
    : "r"(a0), "r"(a1), "r"(a2), "r"(a3), "r"(bl), "r"(bh), "r"(sd));
}
__device__ __forceinline__ void wgmma_rs_48(float (&d)[24], uint32_t a0, uint32_t a1, uint32_t a2, uint32_t a3, uint32_t bl, uint32_t bh, int sd) {
  asm volatile("{\n.reg .pred p;\n.reg .b64 db;\nsetp.ne.b32 p, %30, 0;\nmov.b64 db, {%28, %29};\n"
    "wgmma.mma_async.sync.aligned.m64n48k16.f32.bf16.bf16 {%0,%1,%2,%3,%4,%5,%6,%7,%8,%9,%10,%11,%12,%13,%14,%15,%16,%17,%18,%19,%20,%21,%22,%23}, {%24,%25,%26,%27}, db, p, 1, 1, 1;\n}\n"
    : "+f"(d[0]),"+f"(d[1]),"+f"(d[2]),"+f"(d[3]),"+f"(d[4]),"+f"(d[5]),"+f"(d[6]),"+f"(d[7]),"+f"(d[8]),"+f"(d[9]),"+f"(d[10]),"+f"(d[11]),"+f"(d[12]),"+f"(d[13]),"+f"(d[14]),"+f"(d[15]),"+f"(d[16]),"+f"(d[17]),"+f"(d[18]),"+f"(d[19]),"+f"(d[20]),"+f"(d[21]),"+f"(d[22]),"+f"(d[23])
    : "r"(a0), "r"(a1), "r"(a2), "r"(a3), "r"(bl), "r"(bh), "r"(sd));
}
template<int N,int OFF,int TB> __device__ __forceinline__ void wgmma_ss(float (&d)[96], uint32_t al, uint32_t ah, uint32_t bl, uint32_t bh) {
  if constexpr (N==160 && OFF==0) wgmma_ss_160_0<TB>(d, al, ah, bl, bh);
  else if constexpr (N==144 && OFF==0) wgmma_ss_144_0<TB>(d, al, ah, bl, bh);
  else if constexpr (N==96 && OFF==0) wgmma_ss_96_0<TB>(d, al, ah, bl, bh);
  else if constexpr (N==96 && OFF==48) wgmma_ss_96_48<TB>(d, al, ah, bl, bh);
}

__device__ __forceinline__ void dft3(float2& a, float2& b, float2& c) {
  const float s = 0.86602540378443864676f;
  float2 t = make_float2(b.x + c.x, b.y + c.y), d = make_float2(b.x - c.x, b.y - c.y);
  float2 m = make_float2(fmaf(-0.5f, t.x, a.x), fmaf(-0.5f, t.y, a.y));
  a = make_float2(a.x + t.x, a.y + t.y);
  b = make_float2(fmaf(s, d.y, m.x), fmaf(-s, d.x, m.y));
  c = make_float2(fmaf(-s, d.y, m.x), fmaf(s, d.x, m.y));
}
__device__ __forceinline__ void dft9(float2 (&x)[9]) {
  const float2 w1 = make_float2(0.76604444311897803520f, -0.64278760968653932632f);
  const float2 w2 = make_float2(0.17364817766693034885f, -0.98480775301220805937f);
  const float2 w4 = make_float2(-0.93969262078590838405f, -0.34202014332566873304f);
  dft3(x[0], x[3], x[6]); dft3(x[1], x[4], x[7]); dft3(x[2], x[5], x[8]);
  x[4] = cmul(x[4], w1); x[7] = cmul(x[7], w2); x[5] = cmul(x[5], w2); x[8] = cmul(x[8], w4);
  dft3(x[0], x[1], x[2]); dft3(x[3], x[4], x[5]); dft3(x[6], x[7], x[8]);
  float2 t;
  t = x[1]; x[1] = x[3]; x[3] = t;
  t = x[2]; x[2] = x[6]; x[6] = t;
  t = x[5]; x[5] = x[7]; x[7] = t;
}

__device__ __forceinline__ uint32_t* mod_ptr(Scratch* sc, int u, int t128) {
  const int i = t128 & 15;
  return u < 72 ? sc->moda + (t128 >> 4) * (2 * D_) + 16 * u + 2 * (i & 7) + (i >> 3) : sc->mod + 16 * (u - 72) + i;
}
__device__ __forceinline__ void mod_unit(Scratch* sc, int u, int t128, uint32_t sw_, uint32_t bar, int ph, uint32_t rb, uint32_t tag) {
  const int w = t128 >> 5, l = t128 & 31;
  uint32_t b[18];
#pragma unroll
  for (int i = 0; i < 18; i++) b[i] = lds(red + 512 + (72 * w + 4 * i + (l & 3)) * 4);
  const uint32_t sa = pin(sw_ + (144 * w + (l & 7) + 8 * (l >> 4)) * 32 + (((l >> 3) ^ (l >> 2)) & 1) * 16);
  const uint32_t sr = pin(rb + (l >> 2) * 16 + w * 4);
  uint32_t* const dst = pin(mod_ptr(sc, u, t128));
  const int kind = u / 36;
  const float mul = __uint_as_float(pin(__float_as_uint(kind == 0 ? 16.0f : 1.0f))), add = __uint_as_float(pin(__float_as_uint(kind == 1 || kind == 4 ? 1.0f : 0.0f)));
  mbar_wait(bar, ph);
  if (t128 == 0 && u < 72) TS(10);
  float d[3][4];
#pragma unroll
  for (int i = 0; i < 9; i++) {
    uint32_t a0, a1, a2, a3;
    asm volatile("ldmatrix.sync.aligned.m8n8.x4.trans.shared.b16 {%0,%1,%2,%3}, [%4];" : "=r"(a0), "=r"(a1), "=r"(a2), "=r"(a3) : "r"(sa + i * 512) : "memory");
    if (i < 3) mma16<false>(d[i], a0, a1, a2, a3, b[2 * i], b[2 * i + 1]);
    else mma16<true>(d[i % 3], a0, a1, a2, a3, b[2 * i], b[2 * i + 1]);
  }
  if ((l & 3) == 0) { sts(sr, __float_as_uint(d[0][0] + d[1][0] + d[2][0])); sts(sr + 128, __float_as_uint(d[0][2] + d[1][2] + d[2][2])); }
  bar_sync(4, 128);
  const uint4 v = lds4(rb + (l & 15) * 16);
  const float m = rbf(fmaf(rbf((__uint_as_float(v.x) + __uint_as_float(v.y)) + (__uint_as_float(v.z) + __uint_as_float(v.w))), mul, add));
  if (u < 72 || t128 < 16) *dst = __float_as_uint(m) | tag;
}

__device__ __forceinline__ float rsq(float x) { float r; asm("rsqrt.approx.ftz.f32 %0, %1;" : "=f"(r) : "f"(x)); return r; }
__device__ __forceinline__ void ln_stats2(const float (&a)[18], const float (&b)[18], float sc, float& oa, float& ra, float& ob, float& rb) {
  float v[4] = {0.f, 0.f, 0.f, 0.f}, w[4] = {0.f, 0.f, 0.f, 0.f};
#pragma unroll
  for (int i = 0; i < 18; i += 2) {
    v[0] += a[i]; v[1] = fmaf(a[i], a[i], v[1]); v[2] += b[i]; v[3] = fmaf(b[i], b[i], v[3]);
    w[0] += a[i + 1]; w[1] = fmaf(a[i + 1], a[i + 1], w[1]); w[2] += b[i + 1]; w[3] = fmaf(b[i + 1], b[i + 1], w[3]);
  }
#pragma unroll
  for (int e = 0; e < 4; e++) v[e] += w[e];
#pragma unroll
  for (int o = 16; o; o >>= 1) {
#pragma unroll
    for (int e = 0; e < 4; e++) v[e] += __shfl_xor_sync(0xffffffffu, v[e], o);
  }
  const float ma = v[0] * (1.0f / D_), mb = v[2] * (1.0f / D_);
  ra = sc * rsq(fmaxf(fmaf(-ma, ma, v[1] * (1.0f / D_)), 0.f) + 1e-5f);
  rb = sc * rsq(fmaxf(fmaf(-mb, mb, v[3] * (1.0f / D_)), 0.f) + 1e-5f);
  oa = -ma * ra; ob = -mb * rb;
}

__device__ __forceinline__ float tmat(int c, int q, int j) {
  const int ph = q == 1 ? 1024 * j : (q >> 1) * (c + 128 * j) + 512 * (q & 1);
  return __cosf((float)(((ph + 1024) & 2047) - 1024) * (6.283185307179586f / 2048.0f));
}
__device__ __forceinline__ uint32_t line_off(int k1, int kap, int pi, int f) {
  int kd = 64 * k1 + 9 * kap;
  if (kap == 0 && k1 > 4) kd -= 288;
  if (kd >= D_) kd -= D_;
  return pi * 2400 + ((min(kd, D_ - kd) ^ f) << 3);
}

constexpr int JSK = 5;
struct Ring { uint32_t st, ph; };
template <bool G2, class T> __device__ __forceinline__ void ring_next(T& st, T& ph) {
  if (++st == NST) st = 0;
  ph ^= ((G2 ? 0xDu : 0x1u) >> st) & 1;
}
__device__ __forceinline__ void arrive_if(uint32_t a, uint32_t p) {
  asm volatile("{\n.reg .pred p;\nsetp.ne.u32 p, %1, 0;\n@p mbarrier.arrive.shared::cta.b64 _, [%0];\n}" ::"r"(a), "r"(p) : "memory");
}
template <int NA> __device__ __forceinline__ void reg_fence_n(float (&d)[96]) {
#pragma unroll
  for (int i = 0; i < NA; i++) asm volatile("" : "+f"(d[i])::"memory");
}
template <int MODE>
__device__ __forceinline__ void gemm_main(float (&acc)[96], uint32_t da0, uint32_t da1, uint32_t db0, int wg, Ring& rg,
                                          bool rows, uint32_t* x1p, const uint32_t (&xr)[18]) {
  static_assert(JSK == NST - 1, "the held slot is the first one that is not refilled by GEMM1");
  constexpr int NKB = MODE == 3 ? 36 : 32, J = MODE == 3 ? J2 : JSK;
  constexpr uint32_t HA = 0x40000040u, HB = MODE == 3 ? 0x40000040u : 0x80000020u;
  constexpr uint32_t KA = 2048 >> 4, KB = MODE == 3 ? (32 >> 4) : (1024 >> 4);
  constexpr int NA = MODE == 3 ? 72 : MODE == 1 ? 96 : 80;
  const uint32_t t = threadIdx.x & 127;
  const uint32_t eb = full0 + 8 * NST;
  uint32_t pb = 0, rel = t == 0, prel = 0, ok = 0;
  int n = MODE == 3 ? NKB - J : X1K + 2 * wg;
#pragma unroll 1
  for (int pass = MODE == 3 ? 0 : -1;; pass++) {
#pragma unroll 1
    do {
      const uint32_t so = rg.st * ((MODE == 3 ? STAGE2 : STAGE) >> 4), cb = eb + 8 * rg.st;
      if (__builtin_expect(!ok, 0)) mbar_wait(full0 + 8 * rg.st, rg.ph);
      reg_fence_n<NA>(acc);
      if (MODE == 1 && wg) {
        wg_fence();
#pragma unroll
        for (int k = 0; k < 4; k++) wgmma_ss<96, 48, 1>(acc, da1 + so + k * KA, HA, db0 + so + k * KB, HB);
        wg_commit();
      }
      wg_fence();
#pragma unroll
      for (int k = 0; k < 4; k++) {
        if (k == 3) { ring_next<MODE == 3>(rg.st, rg.ph); ok = PEEK ? mbar_test(full0 + 8 * rg.st, rg.ph) : 0; }
        if (MODE == 0) wgmma_ss<160, 0, 1>(acc, da0 + so + k * KA, HA, db0 + so + k * KB, HB);
        else if (MODE == 3) wgmma_ss<144, 0, 0>(acc, da0 + so + k * KA, HA, db0 + so + k * KB, HB);
        else wgmma_ss<96, 0, 1>(acc, da0 + so + k * KA, HA, db0 + so + k * KB, HB);
      }
      wg_commit();
      wg_wait<1>();
      reg_fence_n<NA>(acc);
      arrive_if(pb, prel);
      pb = cb; prel = rel;
    } while (--n);
    if (pass == 2 - wg) break;
    if (MODE != 3 && pass < 0) {
      if (rows) {
#pragma unroll
        for (int i = 0; i < 9; i++) { x1p[32 * i] = xr[i]; x1p[128 * 288 + 32 * i] = xr[9 + i]; }
      }
      n = NKB - JSK - X1K - 2 * wg;
      continue;
    }
    n = 1;
    if (pass == 0) {
      if (MODE != 3) prel = rel & wg;
      else { rel = 0; if (J < NST) prel = 0; }
      n = J - 1 + wg;
      if (!wg) continue;
      wg_wait<0>();
      arrive_if(pb, prel);
      prel = 0;
    }
    bar_sync(1, 256);
  }
  wg_wait<0>();
  reg_fence_n<NA>(acc);
  if (MODE != 3) arrive_if(pb, MODE == 1 ? prel & ~wg : prel);
}

constexpr float GK1 = 2.0f * 0.7978845608028654f, GK3 = 8.0f * 0.044715f * 0.7978845608028654f;

__device__ __forceinline__ int kb2_order(int i) { const int wv = i / 6; return 6 * (i - 6 * wv) + ((0x431250 >> (4 * wv)) & 7); }

__device__ __forceinline__ int kb2_pos(int kb) { const int hf = kb >= 36, k = kb - 36 * hf, gr = k / 6; return 64 * hf + gr + 6 * ((0x154230 >> (4 * (k - 6 * gr))) & 7); }

__device__ __forceinline__ void wait_flags(const unsigned* p, int idx, unsigned target, uint32_t& ready) {
  int it = 0;
  while (!((ready >> idx) & 1) && it++ < SPIN_MAX) ready = __ballot_sync(0xffffffffu, (int)(ld_rlx(p) - target) >= 0);
}

enum { B_FULL = 0, B_EMPTY = 6, B_S4 = 12, B_S5, B_LAND, B_FLT = B_LAND + 6, B_Z1, B_Z2, B_GO, B_X, B_WM, B_NUM, B_W0 = B_NUM };

__global__ void __launch_bounds__(NTHR, 1)
fused_kernel(const Params p, const __grid_constant__ Maps maps) {
  extern __shared__ __align__(1024) uint8_t smem_raw[];
  const int bx = blockIdx.x, cta = bx < 112 || bx >= 130 ? bx : bx < 114 ? bx + 16 : bx - 2;
  const int tid = threadIdx.x, t128 = tid & 127;
  const int wp = __shfl_sync(0xffffffffu, tid >> 5, 0), wg = wp >> 2;
  const int l = tid & 31, g = l >> 2, t = l & 3;
  Scratch* const sc = p.s;
  const bool rows = cta < 128;
  const int mu = rows ? cta + 4 : cta - 128;
  const int R = mu - 12;

  uint32_t xr[18];
  uint32_t cv[3];
  const unsigned ep0 = ld_rlx(&sc->cnt[C_EP]);
  if (tid == 0) TS(0);
  if (wg == 2) {
#pragma unroll
    for (int i = 0; i < 3; i++) cv[i] = ld_nc(reinterpret_cast<const uint32_t*>(p.c) + min(t128 + 128 * i, 287));
    if (wp == 9 && l < 9 && rows) {
      const int h = 9 * cta + l;
      prefetch_l2(reinterpret_cast<const uint8_t*>(p.wmod) + (size_t)(h >> 1) * (12 * D_) + (h & 1) * (2 * D_), 2 * D_);
    }
    if (tid == 256 && mu < 72) {
      mbar_init(full0 + 8 * B_W0, 1);
      fence_async_smem();
      mbar_expect(full0 + 8 * B_W0, 18432);
#pragma unroll 1
      for (int i = 0; i < 3; i++) tma2d(sbase + O_P2 + i * 6144, &maps.wm, 16 * mu, 192 * i, full0 + 8 * B_W0);
    }
    __syncwarp();
#pragma unroll 1
    for (int u = mu < 72 ? mu : 72 + mu; u < 216; u += u < 72 ? 72 : NCTA) if (u < 72 || t128 < 16) *mod_ptr(sc, u, t128) = 0;
    if (wp == 11 && smem_u32(smem_raw) != sbase) __trap();
    if (wp >= 10 && elect()) {
#pragma unroll 1
      for (int i = wp - 10; i < B_NUM; i += 2) mbar_init(full0 + 8 * i, i == B_FLT ? 4 : i == B_WM ? 3 : i < B_LAND ? 2 : 1);
      fence_async_smem();
    }
    __syncwarp();
  }
  CK(0);
  auto load_x = [&]() {
    const uint32_t* xs = reinterpret_cast<const uint32_t*>(p.x) + (size_t)(cta + 256 * wp) * 288 + l;
#pragma unroll
    for (int i = 0; i < 9; i++) { xr[i] = ld_nc(xs + 32 * i); xr[9 + i] = ld_nc(xs + 128 * 288 + 32 * i); }
  };
  if (rows && wg < 2) load_x();
  if (tid == 64 && cta == NCTA - 1) prefetch_l2(p.tab, sizeof(T_TAB));
  __syncwarp();
  auto tag_of = [](unsigned e) { return (e & 0x7fffu) | 0x8000u; };

  if (wg == 2) {
#pragma unroll
    for (int i = 0; i < 3; i++) {
      const float c0 = bf_lo(cv[i]), c1 = bf_hi(cv[i]);
      sts(red + 512 + min(t128 + 128 * i, 287) * 4, pack_bf16(__fdividef(c0, 1.0f + __expf(-c0)), __fdividef(c1, 1.0f + __expf(-c1))));
    }
    if (t128 == 0) sts(full0 + 248, ep0 + 1);
    if (wp == 9 && l < 12) asm volatile("prefetch.tensormap [%0];" ::"l"(&maps.z1 + l) : "memory");
    bar_sync(4, 128);
    if (mu < 72) {
      mod_unit(sc, mu, t128, sbase + O_P2, full0 + 8 * B_W0, 0, red, tag_of(upin(ep0) + 1));
      if (t128 == 0) TS(25);
    }
    CK(1);
  }
  const int pi = R / 15, col0 = 20 * (R - 15 * pi);
  const int xu = DF_ * pi + col0, xv = DF_ * (pi ? 16 - pi : 8) + col0;
  auto load_filter = [&](int a) {
    const int x = (a & 1) ? xv : xu;
    const bool wide = (x & 15) > 12;
    mbar_expect(full0 + 8 * B_FLT, wide ? 12288 : 8192);
    tma2d(sbase + O_RAW + a * 12288, &maps.wf[a & 2], x & ~15, 0, full0 + 8 * B_FLT);
    if (wide) tma2d(sbase + O_RAW + a * 12288 + 8192, &maps.wf[(a & 2) + 1], (x & ~15) + 32, 0, full0 + 8 * B_FLT);
  };
  const int kap = 8 * ((wp & 3) ^ (wg & 1)) + g;
  uint4 af[4];
  if (rows) {
    uint32_t tb[4];
#pragma unroll
    for (int i = 0; i < 4; i++) tb[i] = pack_bf16(tmat(cta, 8 * (i >> 1) + g, 2 * t + 8 * (i & 1)), tmat(cta, 8 * (i >> 1) + g, 2 * t + 8 * (i & 1) + 1));
    uint32_t sb1[3], lo[9];
#pragma unroll
    for (int i = 0; i < 4; i++) tb[i] = pin(tb[i]);
#pragma unroll
    for (int i = 0; i < 3; i++) {
      const int d = 48 * wp + 16 * i + (l & 15);
      sb1[i] = pin(sbase + O_B1 + (l >> 4) * 9216 + (d % 9) * 1024 + (d & 63) * 16);
    }
    const uint32_t snt = pin(sbase + O_NRM + ((l & 7) + 8 * (l >> 4)) * 1168 + (48 * wp + (l & 8)) * 2);
    uint2 ms[3], mc[3];
    const uint32_t smask = pin(t ? 0u : 0xffff0000u);
    const uint32_t* const mp = pin(sc->moda + (cta >> 4) * (2 * D_) + 48 * wp + 2 * g);
    auto load_mod = [&]() {
#pragma unroll
      for (int i = 0; i < 3; i++) { ms[i] = ld_rlx2(mp + 16 * i); mc[i] = ld_rlx2(mp + D_ + 16 * i); }
    };
    if (wg < 2) {
#pragma unroll
      for (int k1 = 0; k1 < 9; k1++) lo[k1] = pin(sbase + O_Z1 + line_off(k1, kap, 4 * wg + t, cta & 3));
      float a[18], b[18];
#pragma unroll
      for (int i = 0; i < 9; i++) { a[2 * i] = bf_lo(xr[i]); a[2 * i + 1] = bf_hi(xr[i]); b[2 * i] = bf_lo(xr[9 + i]); b[2 * i + 1] = bf_hi(xr[9 + i]); }
      float oa, ra, ob, rb;
      ln_stats2(a, b, 1.0f, oa, ra, ob, rb);
      CK(1);
      const uint32_t sn = sbase + O_NRM + wp * 2336 + l * 4;
#pragma unroll
      for (int i = 0; i < 9; i++) {
        sts(sn + i * 128, pack_bf16(fmaf(a[2 * i], ra, oa), fmaf(a[2 * i + 1], ra, oa)));
        sts(sn + 1168 + i * 128, pack_bf16(fmaf(b[2 * i], rb, ob), fmaf(b[2 * i + 1], rb, ob)));
      }
      CK(2);
      bar_arrive(10, NTHR);
      load_mod();
#pragma unroll
      for (int kk = 0; kk < 4; kk++) af[kk] = ld_nc4(p.tab + TB_F + kk * 128 + (t128 ^ (wg << 5)));
      bar_sync(1, 256);
      if (tid == 0) TS(2);
    } else {
      bar_sync(10, NTHR);
      load_mod();
      CK(2);
      if (PFF && wp >= 12 - PFF && elect()) prefetch_l2(reinterpret_cast<const uint8_t*>(wp == 10 ? p.wr : p.wi) + cta * 9248, 9248);
      __syncwarp();
    }
    float rs[3][8];
#pragma unroll
    for (int i = 0; i < 3; i++) {
      uint32_t a0, a1, a2, a3;
      asm volatile("ldmatrix.sync.aligned.m8n8.x4.trans.shared.b16 {%0,%1,%2,%3}, [%4];" : "=r"(a0), "=r"(a1), "=r"(a2), "=r"(a3)
                   : "r"(snt + 32 * i) : "memory");
      mma16<false>(&rs[i][0], a0, a1, a2, a3, tb[0], tb[1]);
      mma16<false>(&rs[i][4], a0, a1, a2, a3, tb[2], tb[3]);
    }
    CK(3);
    const uint32_t tag16 = tag_of(upin(ep0) + 1), tag1 = tag16 & 1;
    {
      int it = 0;
#pragma unroll 1
      while (true) {
        uint32_t bad = 0;
#pragma unroll
        for (int i = 0; i < 3; i++) bad |= diff2(ms[i].x, ms[i].y, tag16) | diff2(mc[i].x, mc[i].y, tag16);
        if (!any(bad & 0xffffu) || ++it > SPIN_MAX) break;
        load_mod();
      }
      CK(4);
      if (tid == 0) TS(3);
#pragma unroll
      for (int i = 0; i < 3; i++) {
        const float c0 = bf_hi(mc[i].x), c1 = bf_hi(mc[i].y);
        const float s0 = __uint_as_float(ms[i].x & smask), s1 = __uint_as_float(ms[i].y & smask);
        stmatrix4(sb1[i], pack_bf16(fmaf(rs[i][0], c0, s0), rs[i][1] * c0), pack_bf16(fmaf(rs[i][2], c1, s1), rs[i][3] * c1),
                  pack_bf16(rs[i][4] * c0, rs[i][5] * c0), pack_bf16(rs[i][6] * c1, rs[i][7] * c1));
      }
    }
    fence_async_smem();
    CK(5);
    if (wg == 2) {
      bar_arrive(5, NTHR);
      if (R >= 0 && elect()) load_filter(wp - 8);
      __syncwarp();
    } else {
      bar_sync(5, NTHR);
      CK(6);
      float acc[36];
      const uint32_t db = (((sbase + O_B1 + wg * 9216) & 0x3FFFF) >> 4) | ((128 >> 4) << 16);
      wg_fence();
#pragma unroll
      for (int kk = 0; kk < 4; kk++) wgmma_rs_72(acc, af[kk].x, af[kk].y, af[kk].z, af[kk].w, db + kk * 16, 1024 >> 4, kk);
      wg_commit();
      wg_wait<0>();
      reg_fence(acc);
      CK(7);
      float2 za[9], zb[9];
#pragma unroll
      for (int i = 0; i < 9; i++) { za[i] = make_float2(acc[4 * i], acc[4 * i + 2]); zb[i] = make_float2(acc[4 * i + 1], acc[4 * i + 3]); }
      dft9(za); dft9(zb);
      if (kap == 0) {
#pragma unroll
        for (int k = 1; k < 5; k++) {
          float2 a = za[k], b = za[9 - k];
          za[k] = make_float2(a.x + b.x, a.y - b.y); za[9 - k] = make_float2(a.y + b.y, b.x - a.x);
          a = zb[k]; b = zb[9 - k];
          zb[k] = make_float2(a.x + b.x, a.y - b.y); zb[9 - k] = make_float2(a.y + b.y, b.x - a.x);
        }
        sts2(lo[0] + 288 * 8, set_tag(pack_bf16(za[0].y, 0.f), tag1), pack_bf16(zb[0].y, 0.f));
        za[0].y = 0.f; zb[0].y = 0.f;
      }
      __syncwarp();
#pragma unroll
      for (int k1 = 0; k1 < 9; k1++) sts2(lo[k1], set_tag(pack_bf16(za[k1].x, za[k1].y), tag1), pack_bf16(zb[k1].x, zb[k1].y));
      fence_async_smem();
      CK(8);
      bar_arrive(2 + wg, 160);
      {
        const uint32_t fx = (((cta >> 4) ^ cta) & 3) << 3, dl = O_IN - O_Z1, st = sbase + O_ST + 15360 + tid * 16;
        sts4(st, (lo[0] ^ fx) + dl, (lo[1] ^ fx) + dl, (lo[2] ^ fx) + dl, (lo[3] ^ fx) + dl);
        sts4(st + 4096, (lo[4] ^ fx) + dl, (lo[5] ^ fx) + dl, (lo[6] ^ fx) + dl, (lo[7] ^ fx) + dl);
        sts4(st + 8192, (lo[8] ^ fx) + dl, (lo[0] ^ fx) + dl + (kap ? 0 : 288 * 8),
             sbase + O_B3 + wg * 1024 + (l >> 4) * 2048 + (2 * (kap & 24) + (l & 15)) * 16, 0);
      }
    }
    {
      uint32_t sy[6];
#pragma unroll
      for (int i = 0; i < 6; i++) {
        const int rr = 16 * (wp & 3) + g + 8 * (i & 1);
        sy[i] = sbase + O_Y + (t * 584 + 64 * ((3 * wg + (i >> 1) + 63 - rr) % 9) + rr) * 4;
      }
      sts4(sbase + O_ST + tid * 16, movm(tb[0]), movm(tb[2]), movm(tb[1]), movm(tb[3]));
      sts4(sbase + O_ST + 6144 + tid * 16, sy[0], sy[1], sy[2], sy[3]);
      sts2(sbase + O_ST + 12288 + tid * 8, sy[4], sy[5]);
    }
  } else {
    __syncthreads();
  }

  const unsigned ep = upin(lds(full0 + 248));
  const uint32_t tag16 = tag_of(ep), tag1 = ep & 1;
  if ((wp >> 1) == 4) {
    if (rows) {
      const int slot = 4 * (cta & 7) + ((cta >> 4) & 3) + 32 * (2 * (cta >> 6) + ((cta >> 3) & 1));
      const uint32_t c0 = upin(40 * slot), c1 = upin(60 * (wp - 8)), src = upin(sbase + O_Z1 + (wp - 8) * 9600);
      const CUtensorMap* mp = upin(&maps.z1);
      unsigned* hint = pin(sc->cnt + C_Z1 + 32 * (wp - 8));
      bar_sync(wp - 6, 160);
      if (elect()) tma_st2d(mp, src, c0, c1);
      bulk_commit_wait();
      if (elect()) red_add(hint, 1);
      if (tid == 256) TS(4);
    }
    __syncwarp();
  }
  auto load_wm = [&](int u) {
    if (wp > 8 && elect()) {
      mbar_expect(full0 + 8 * B_WM, 6144);
      tma2d(sbase + O_NRM + (wp - 9) * 6144, &maps.wm, 16 * u, 192 * (wp - 9), full0 + 8 * B_WM);
    }
    __syncwarp();
  };
  if (R >= 0) {
    const int nl = (col0 + wp < DF_) + (wg < 2 && col0 + wp + 12 < DF_);
    uint4 cf[2][4], G[4];
#pragma unroll
    for (int i = 0; i < 4; i++) {
      cf[0][i] = __ldg(p.tab + TB_P2 + i * 32 + l);
      cf[1][i] = __ldg(p.tab + TB_P2 + (pi ? i : 4 + i) * 32 + l);
      G[i] = __ldg(p.tab + TB_P2 + (8 + i) * 32 + l);
    }
    const uint32_t* zin = sc->z1 + (size_t)R * 5120;
    if (wp == 10) {
      const uint32_t* zu = upin(zin);
      if (elect()) mbar_expect(full0 + 8 * B_Z1, 20480);
      wait_cnt(sc->cnt + C_Z1 + 32 * (pi >> 2), 128 * ep);
      if (elect()) {
        bulk_ld(sbase + O_P2, zu, 20480, full0 + 8 * B_Z1);
        TS(12);
      }
      __syncwarp();
    }
    mbar_wait(full0 + 8 * B_FLT, 0);
    CK(9);
    float wn[16], wc[16];
#pragma unroll 1
    for (int ln = nl - 1; ln >= 0; ln--) {
      const int col = col0 + wp + 12 * ln, k2 = (57 * col) & 63;
      const bool cj = k2 > 32 || (k2 == 32 && col != 288);
      const float nr = ((col & 31) == 0 && col != 0 && col != 288 ? 0.5f : 1.0f) / ((float)S_ * D_), ni = cj ? -nr : nr;
#pragma unroll
      for (int i = 0; i < 16; i++) wn[i] = wc[i];
#pragma unroll
      for (int cl = 0; cl < 2; cl++) {
        const int v = cl ^ (cj && pi), e = ((v ? xv : xu) & 15) + wp + 12 * ln, sh = e < 32 ? 6 : 5;
        const uint32_t base = sbase + O_RAW + v * 12288 + (e < 32 ? 2 * e : 8192 - 64 + 2 * e), msk = e < 32 ? 0x30 : 0x10;
        const int dm = v ? (cj || pi ? -1 : 0) : 0;
#pragma unroll
        for (int tt = 0; tt < 4; tt++) {
          const int kc = g + 64 * (tt >> 1) + 16 * t + 8 * (tt & 1);
          uint32_t a = base + ((((cj ? -kc : kc) + dm) & 127) << sh);
          a ^= (a >> 3) & msk;
          wc[4 * tt + 2 * cl] = lds_bf(a) * nr; wc[4 * tt + 2 * cl + 1] = lds_bf(a + 24576) * ni;
        }
      }
    }
    const float al = __uint_as_float(pin((pi ? 0x3f800000u : 0u) + (l >> 5)));
    const uint32_t tagv = pin(tag1 + (l >> 5));
    CK(10);
    uint32_t off = pin(l * 160 + ((wp ^ (g & 3)) << 3));
    uint32_t offo = pin(sbase + O_P2 + 20480 + off - 64 * l), po = 3072;
    unsigned* hz2 = pin(sc->cnt + C_Z2);
    const uint32_t do2 = pin(12288 - 32 * l);
    const CUtensorMap* mz2 = upin(&maps.z2[wp == 0]);
    const uint32_t sz2 = upin(sbase + O_P2 + 20480 + (wp ? 0 : 12288)), cz2 = upin(40 * R + (wp ? 0 : 24));
    mbar_wait(full0 + 8 * B_Z1, 0);
    CK(11);
    if (tid == 0) TS(8);
    if (wg == 2) load_wm(72 + mu);
    uint2 v[4], v2[4];
    const uint32_t o2 = nl > 1 ? 96 : 0;
#pragma unroll
    for (int i = 0; i < 4; i++) { v[i] = lds2(sbase + O_P2 + off + i * 5120); v2[i] = lds2(sbase + O_P2 + off + o2 + i * 5120); }
    auto bad2 = [&]() {
      return any(or3(or3(diff2(v[0].x, v[1].x, tagv), diff2(v[2].x, v[3].x, tagv), diff2(v2[0].x, v2[1].x, tagv)), diff2(v2[2].x, v2[3].x, tagv), 0) & 1);
    };
    if (__builtin_expect(bad2() && nl, 0)) {
      FAILCNT(0);
      int it = 0;
      do {
#pragma unroll
        for (int i = 0; i < 4; i++) {
          v[i] = ld_rlx2(reinterpret_cast<const uint8_t*>(zin) + off + i * 5120);
          v2[i] = ld_rlx2(reinterpret_cast<const uint8_t*>(zin) + off + o2 + i * 5120);
        }
      } while (bad2() && ++it < SPIN_MAX);
    }
#pragma unroll 1
    for (int ln = 0; ln < nl; ln++, offo += do2, po = 2048) {
      float d[4][4];
      uint32_t A[8];
#pragma unroll
      for (int h = 0; h < 2; h++) {
        mma16<false>(d[2 * h], cf[0][0].x, cf[0][0].y, cf[0][0].z, cf[0][0].w, v[h].x, v[2 + h].x);
        mma16<false>(d[2 * h + 1], cf[1][0].x, cf[1][0].y, cf[1][0].z, cf[1][0].w, v[h].y, v[2 + h].y);
      }
      if (ln) { fence_async_smem(); bar_arrive(15, NTHR); }
#pragma unroll
      for (int h = 0; h < 2; h++)
#pragma unroll
        for (int L = 0; L < 2; L++) {
          const uint4 tw = cf[L][2 + h];
          const float* z = d[2 * h + L];
          const float2 z0 = cmul(make_float2(z[0], z[2]), make_float2(__uint_as_float(tw.x), __uint_as_float(tw.y)));
          const float2 z1 = cmul(make_float2(z[1], z[3]), make_float2(__uint_as_float(tw.z), __uint_as_float(tw.w)));
          A[4 * h + L] = pack_bf16(z0.x, z0.y); A[4 * h + 2 + L] = pack_bf16(z1.x, z1.y);
        }
#pragma unroll
      for (int tt = 0; tt < 4; tt++) {
        mma16<false>(d[tt], A[0], A[1], A[2], A[3], G[tt].x, G[tt].y);
        mma16<true>(d[tt], A[4], A[5], A[6], A[7], G[tt].z, G[tt].w);
      }
#pragma unroll
      for (int tt = 0; tt < 4; tt++) {
        const float ar = d[tt][0], aj = d[tt][1], br = d[tt][2], bj = d[tt][3];
        const float2 y1 = cmul(make_float2(fmaf(-al, bj, ar), fmaf(al, br, aj)), make_float2(wc[4 * tt], wc[4 * tt + 1]));
        const float2 y2 = cmul(make_float2(fmaf(al, ar, bj), fmaf(al, aj, -br)), make_float2(wc[4 * tt + 2], wc[4 * tt + 3]));
        A[2 * tt] = pack_bf16(fmaf(al, y2.x, y1.x), fmaf(-al, y2.y, -y1.y));
        A[2 * tt + 1] = pack_bf16(fmaf(al, y1.y, -y2.y), fmaf(al, y1.x, -y2.x));
      }
#pragma unroll
      for (int i = 0; i < 16; i++) wc[i] = wn[i];
#pragma unroll
      for (int i = 0; i < 4; i++) v[i] = v2[i];
#pragma unroll
      for (int tt = 0; tt < 4; tt++) {
        mma16<false>(d[tt], A[0], A[1], A[2], A[3], G[tt].x, G[tt].y);
        mma16<true>(d[tt], A[4], A[5], A[6], A[7], G[tt].z, G[tt].w);
      }
#pragma unroll
      for (int h = 0; h < 2; h++)
#pragma unroll
        for (int L = 0; L < 2; L++) {
          const uint4 tw = cf[L][2 + h];
          const float2 z0 = cmul(make_float2(d[2 * h][2 * L], d[2 * h][2 * L + 1]), make_float2(__uint_as_float(tw.x), __uint_as_float(tw.y)));
          const float2 z1 = cmul(make_float2(d[2 * h + 1][2 * L], d[2 * h + 1][2 * L + 1]), make_float2(__uint_as_float(tw.z), __uint_as_float(tw.w)));
          A[4 * h + 2 * L] = movm(pack_bf16(z0.x, z1.x)); A[4 * h + 2 * L + 1] = movm(pack_bf16(z0.y, z1.y));
        }
#pragma unroll
      for (int h = 0; h < 2; h++) {
        mma16<false>(d[0], cf[0][1].x, cf[0][1].y, cf[0][1].z, cf[0][1].w, A[4 * h], A[4 * h + 1]);
        mma16<false>(d[1], cf[1][1].x, cf[1][1].y, cf[1][1].z, cf[1][1].w, A[4 * h + 2], A[4 * h + 3]);
#pragma unroll
        for (int e = 0; e < 2; e++)
          sts2(offo + (2 * h + e) * po, set_tag(pack_bf16(d[0][e], d[0][2 + e]), tagv), pack_bf16(d[1][e], d[1][2 + e]));
      }
      CK(12 + ln);
    }
    fence_async_smem();
    if (nl < 2 && wp != 8) bar_arrive(15, NTHR);
    if (wp & 7) { if (wg < 2) bar_arrive(6, 256); }
    else {
      if (wp) bar_sync(15, NTHR); else bar_sync(6, 256);
      if (elect()) tma_st2d(mz2, sz2, cz2, 0);
      bulk_commit_wait();
      if (wp == 0 && elect()) red_add(hz2, 1);
      if (tid == 0) TS(9);
      __syncwarp();
    }
  }
  if (wg == 2) {
#pragma unroll 1
    for (int u = 72 + mu, k = 0; u < 216; u += NCTA, k ^= 1) {
      if (R < 0) { fence_async_smem(); bar_sync(4, 128); load_wm(u); }
      mod_unit(sc, u, t128, sbase + O_NRM, full0 + 8 * B_WM, k, red + 256 - 256 * k, tag16);
    }
    fence_async_smem();
    CK(13);
  }

  const int grp = bx / 11, m1 = bx - 11 * grp;
  const bool helper = (m1 & 3) == 3;
  const int f1 = 384 * grp + (helper ? 192 : 128) * (m1 >> 2);
  const int d1 = 160 * (m1 & 3), flip = m1 >= 7;
  const int a1bytes = helper ? 24576 : 16384;
  auto load_a1 = [&](int st, int kb) {
    mbar_expect(full0 + 8 * st, a1bytes);
    tma4d_ef(sbase + st * STAGE, helper ? &maps.w1b : &maps.w1a, 4 * (kb >> 3), 16 * (kb & 7), f1 >> 6, full0 + 8 * st);
  };

  if (rows) {
#pragma unroll
    for (int kk = 0; kk < 4; kk++) af[kk] = __ldg(p.tab + TB_E + kk * 128 + t128);
    const uint4 c0 = lds4(sbase + O_ST + tid * 16), c1 = lds4(sbase + O_ST + 6144 + tid * 16);
    const uint2 c2 = lds2(sbase + O_ST + 12288 + tid * 8);
    const uint32_t tb[4] = {c0.x, c0.y, c0.z, c0.w}, sy[6] = {c1.x, c1.y, c1.z, c1.w, c2.x, c2.y};
    const uint32_t l8 = pin(8 * l), syl = pin(sbase + O_Y + wp * 2336 + 8 * l);
    uint32_t sh3[3], ham[3];
#pragma unroll
    for (int k = 0; k < 3; k++) {
      const int pos = k && (l >> 4) == k - 1 ? (l & 8) + 4 * (l & 1) + ((l >> 1) & 3) : 4 * (l & 3) + ((l >> 2) & 3);
      const int sw = 2 * cta + (wp & 1), ph = pos ^ ((sw & 3) << 2);
      sh3[k] = pin(sbase + O_B3 + (wp >> 1) * 4608 + (l >> 4) * 256 + (wp & 1) * 128 + ph * 4);
      const bool tg = ((ph ^ sw) & 7) == 0;
      ham[k] = pin(tg ? ~1u : ~0u);
    }
    const int slot = 4 * (cta >> 4) + ((cta >> 1) & 3) + 32 * (2 * ((cta >> 3) & 1) + (cta & 1));
    const uint32_t* zin = sc->z2 + (size_t)slot * 4800;
    uint32_t ga[9];
    uint2 sh[9], sw[9];
    auto load_mod3 = [&](int part) {
#pragma unroll
      for (int i = 0; i < 9; i++) {
        if (part != 2) { const uint2 v = lds2(l8 + sbase + O_MOD + 256 * i); ga[i] = __byte_perm(v.x, v.y, 0x7632); }
        if (part != 1) { sh[i] = lds2(l8 + sbase + O_MOD + 4 * D_ + 256 * i); sw[i] = lds2(l8 + sbase + O_MOD + 8 * D_ + 256 * i); }
      }
    };
    if (wg == 2) {
      {
        uint4 v[4];
        const int i3 = min(t128 + 384, 431);
        int it = 0;
        while (true) {
          uint32_t bad = 0;
#pragma unroll
          for (int k = 0; k < 4; k++) v[k] = ld_rlx4(sc->mod + 4 * (k < 3 ? t128 + 128 * k : i3));
#pragma unroll
          for (int k = 0; k < 4; k++) {
            v[k].x ^= tag16; v[k].y ^= tag16; v[k].z ^= tag16; v[k].w ^= tag16;
            bad |= v[k].x | v[k].y | v[k].z | v[k].w;
          }
          if (!any(bad & 0xffffu) || ++it > SPIN_MAX) break;
        }
#pragma unroll
        for (int k = 0; k < 4; k++) sts4(sbase + O_MOD + 16 * (k < 3 ? t128 + 128 * k : i3), v[k].x, v[k].y, v[k].z, v[k].w);
      }
      CK(14);
      bar_sync(10, NTHR);
      mbar_wait(full0 + 8 * B_Z2, 0);
      if (elect()) {
        load_a1(wp - 8, wp - 8);
        if (wp > 8 && wp - 8 < NG1) prefetch_l2(reinterpret_cast<const uint8_t*>(p.w1) + (size_t)(128 * (4 * ((wp - 8) >> 1) + (cta >> 5)) + 64 * (wp & 1) + 2 * (cta & 31)) * (2 * F_), 4 * F_);
      }
      __syncwarp();
    } else {
      const uint4 e0 = lds4(sbase + O_ST + 15360 + tid * 16), e1 = lds4(sbase + O_ST + 19456 + tid * 16), e2 = lds4(sbase + O_ST + 23552 + tid * 16);
      const uint32_t lo[9] = {e0.x, e0.y, e0.z, e0.w, e1.x, e1.y, e1.z, e1.w, e2.x}, lx = e2.y, sb3 = e2.z;
      if (MODPOS == 0) bar_arrive(10, NTHR);
      CK(14);
      if (wp == 1) {
        const uint32_t* zu = upin(zin);
        if (elect()) mbar_expect(full0 + 8 * B_Z2, 19200);
        wait_cnt(sc->cnt + C_Z2, 120 * ep);
        if (elect()) {
          bulk_ld(sbase + O_IN, zu, 19200, full0 + 8 * B_Z2);
          TS(14);
        }
        __syncwarp();
      }
      if (MODPOS) { bar_sync(10, NTHR); load_mod3(MODPOS - 1); }
      mbar_wait(full0 + 8 * B_Z2, 0);
      CK(15);
      if (tid == 0) TS(11);
      uint2 v[10];
#pragma unroll
      for (int k1 = 0; k1 < 10; k1++) v[k1] = lds2(k1 < 9 ? lo[k1] : lx);
      auto bad3 = [&]() {
        return any(or3(or3(diff2(v[0].x, v[1].x, tag1), diff2(v[2].x, v[3].x, tag1), diff2(v[4].x, v[5].x, tag1)), diff2(v[6].x, v[7].x, tag1), diff2(v[8].x, v[9].x, tag1)) & 1);
      };
      if (__builtin_expect(bad3(), 0)) {
        FAILCNT(1);
        int it = 0;
        do {
#pragma unroll
          for (int k1 = 0; k1 < 10; k1++) v[k1] = ld_rlx2(reinterpret_cast<const uint8_t*>(zin) + ((k1 < 9 ? lo[k1] : lx) - (sbase + O_IN)));
        } while (bad3() && ++it < SPIN_MAX);
      }
      float2 za[9], zb[9];
#pragma unroll
      for (int i = 0; i < 9; i++) { za[i] = make_float2(bf_lo(v[i].x), bf_hi(v[i].x)); zb[i] = make_float2(bf_lo(v[i].y), bf_hi(v[i].y)); }
      if (kap == 0) {
#pragma unroll
        for (int k = 1; k < 5; k++) {
          float2 a = za[k], b = za[9 - k];
          za[k] = make_float2(a.x - b.y, a.y + b.x); za[9 - k] = make_float2(a.x + b.y, b.x - a.y);
          a = zb[k]; b = zb[9 - k];
          zb[k] = make_float2(a.x - b.y, a.y + b.x); zb[9 - k] = make_float2(a.x + b.y, b.x - a.y);
        }
        za[0].y = bf_lo(v[9].x); zb[0].y = bf_lo(v[9].y);
      }
      __syncwarp();
      dft9(za); dft9(zb);
#pragma unroll
      for (int n = 0; n < 8; n += 2) {
        const int i0 = (9 - n) % 9, i1 = 8 - n;
        stmatrix4(sb3 + n * 2048, pack_bf16(za[i0].x, zb[i0].x), pack_bf16(za[i0].y, zb[i0].y), pack_bf16(za[i1].x, zb[i1].x), pack_bf16(za[i1].y, zb[i1].y));
      }
      stmatrix2(sb3 + 8 * 2048, pack_bf16(za[1].x, zb[1].x), pack_bf16(za[1].y, zb[1].y));
      fence_async_smem();
    }
    CK(16);
    __syncthreads();
    CK(17);
    float acc[24];
    const uint32_t db = (((sbase + O_B3 + wg * 6144) & 0x3FFFF) >> 4) | ((128 >> 4) << 16);
    wg_fence();
#pragma unroll
    for (int kk = 0; kk < 4; kk++) wgmma_rs_48(acc, af[kk].x, af[kk].y, af[kk].z, af[kk].w, db + kk * 16, 1024 >> 4, kk);
    wg_commit();
    if (wg < 2 && MODPOS == 0) load_mod3(0);
    wg_wait<0>();
    reg_fence(acc);
    CK(18);
#pragma unroll
    for (int i = 0; i < 3; i++) {
      const float* a = &acc[8 * i];
      const uint32_t a0 = pack_bf16(a[0], a[1]), a1 = pack_bf16(a[2], a[3]), a2 = pack_bf16(a[4], a[5]), a3 = pack_bf16(a[6], a[7]);
#pragma unroll
      for (int jh = 0; jh < 2; jh++) {
        float y[4];
        mma16<false>(y, a0, a1, a2, a3, tb[2 * jh], tb[2 * jh + 1]);
        sts(sy[2 * i] + jh * (4 * 584 * 4), pack_bf16(y[0], y[1]));
        sts(sy[2 * i + 1] + jh * (4 * 584 * 4), pack_bf16(y[2], y[3]));
      }
    }
    CK(19);
    if (wg == 2) { bar_arrive(7, NTHR); if (W2H) bar_sync(15, NTHR); }
    else {
      bar_sync(7, NTHR);
      CK(20);
      float a[18], b[18];
#pragma unroll
      for (int i = 0; i < 9; i++) {
        const uint2 y = lds2(syl + 256 * i);
        xr[i] = hfma2(ga[i], __byte_perm(y.x, y.y, 0x5410), xr[i]);
        xr[9 + i] = hfma2(ga[i], __byte_perm(y.x, y.y, 0x7632), xr[9 + i]);
        a[2 * i] = bf_lo(xr[i]); a[2 * i + 1] = bf_hi(xr[i]); b[2 * i] = bf_lo(xr[9 + i]); b[2 * i + 1] = bf_hi(xr[9 + i]);
      }
      float oa, ra, ob, rb;
      if (MODPOS == 2) load_mod3(2);
      ln_stats2(a, b, 1.0f, oa, ra, ob, rb);
      CK(21);
      if (W2H == 1) bar_arrive(15, NTHR);
#pragma unroll
      for (int i = 0; i < 9; i++) {
        const float c0 = __uint_as_float(sw[i].x), c1 = __uint_as_float(sw[i].y), s0 = __uint_as_float(sh[i].x), s1 = __uint_as_float(sh[i].y);
        a[2 * i] = fmaf(fmaf(a[2 * i], ra, oa), c0, s0); a[2 * i + 1] = fmaf(fmaf(a[2 * i + 1], ra, oa), c1, s1);
        b[2 * i] = fmaf(fmaf(b[2 * i], rb, ob), c0, s0); b[2 * i + 1] = fmaf(fmaf(b[2 * i + 1], rb, ob), c1, s1);
      }
      ln_stats2(a, b, 0.5f, oa, ra, ob, rb);
      CK(22);
      if (W2H == 2) bar_arrive(15, NTHR);
#pragma unroll
      for (int i = 0; i < 9; i++) {
        const int k = i == 2 ? 1 : i == 6 ? 2 : 0;
        sts(sh3[k] + i * 512, bitsel(pack_bf16(fmaf(a[2 * i], ra, oa), fmaf(a[2 * i + 1], ra, oa)), ham[k], tag1));
        sts(sh3[k] + i * 512 + 64, bitsel(pack_bf16(fmaf(b[2 * i], rb, ob), fmaf(b[2 * i + 1], rb, ob)), ham[k], tag1));
      }
      fence_async_smem();
      if (wp < 2 * H3G) bar_arrive(8, 32 + 64 * H3G); else bar_arrive(9, 288 - 64 * H3G);
      CK(23);
    }
  }

  const bool g2 = rows;
  const int z2 = cta, r = z2 >> 6;
  const int s2 = 128 * ((z2 >> 2) & 15), d2 = 144 * (z2 & 3);
  constexpr int ST0 = (32 - JSK - 1) % NST, ST1 = 31 % NST;

  if (wg == 2) {
    asm volatile("setmaxnreg.dec.sync.aligned.u32 40;");
    auto load_b = [&](bool second, int i, int st) {
      const uint32_t lb = full0 + 8 * (B_LAND + st), bytes = second ? 18432 : STAGE - a1bytes;
      mbar_expect(lb, bytes);
      bulk_ld(sbase + (second ? st * STAGE2 + 16384 : st * STAGE + a1bytes),
              second ? sc->u + ((size_t)(36 * r + kb2_order(i)) * D_ + d2) * 128 : sc->h3 + ((size_t)(i * 18 + (d1 >> 5)) << 12), bytes, lb);
    };
    if (wp == 8) {
      int st = rows ? 4 : 0, ph = 1;
#pragma unroll 1
      for (int kb = st; kb < 32; kb++) {
        if (rows && (kb >> 1) == 2) mbar_wait(full0 + 8 * (B_S4 - 4 + kb), 0);
        mbar_wait(empty0 + 8 * st, ph);
        if (elect()) {
          load_a1(st, kb);
          if (kb >= PF2K && kb < PF2K + PF2 && g2)
            prefetch_l2(reinterpret_cast<const uint8_t*>(p.w2) + (size_t)(36 * r + kb2_order(kb - PF2K)) * 262144 + (z2 & 63) * 4096, 4096);
        }
        __syncwarp();
        ring_next<false>(st, ph);
      }
      if (g2) {
        st++;
#pragma unroll 1
        for (int i = 0; i < 36; i++) {
          if (i == HOLDA) mbar_wait(full0 + 8 * B_GO, 0);
          mbar_wait(empty0 + 8 * st, ph);
          if (elect()) {
            mbar_expect(full0 + 8 * st, 16384);
            tma3d_ef(sbase + st * STAGE2, &maps.w2, 64 * (36 * r + kb2_order(i)), s2 >> 6, full0 + 8 * st);
          }
          __syncwarp();
          ring_next<true>(st, ph);
        }
      }
    } else if (wp >= 10) {
      const int sw = wp - 10;
      if (rows) {
        const CUtensorMap* mp = upin(&maps.h3[sw]);
        const uint32_t src = upin(sbase + O_B3 + sw * (H3G * 4608)), c0 = upin(64 * (cta & 15)), c1 = upin(18 * (cta >> 4)), c2 = upin(H3G * sw);
        unsigned* flag = pin(sc->cnt + C_H3 + (cta >> 4) + 8 * sw);
        bar_sync(8 + sw, sw ? 288 - 64 * H3G : 32 + 64 * H3G);
        if (sw) mbar_wait(full0 + 8 * H3W, 0);
        if (elect()) { tma_st3d(mp, src, c0, c1, c2); mbar_arrive(full0 + 8 * B_S4); }
        bulk_commit_wait();
        if (elect()) red_add(flag, 1);
        if (elect()) { mbar_arrive(full0 + 8 * B_S5); TS(sw ? 24 : 13); }
        __syncwarp();
      }
      if (sw) {
        if (rows) {
          mbar_wait(full0 + 8 * B_S5, 0);
          if (elect()) { asm volatile("fence.acq_rel.gpu;" ::: "memory"); red_add(&sc->cnt[C_X + 64], 1); }
          __syncwarp();
        }
        if (g2) {
          uint2 v[3];
          int it = 0;
          do {
#pragma unroll
            for (int i = 0; i < 3; i++) v[i] = ld_rlx2(sc->mod + 3 * D_ + d2 + 2 * min(l + 32 * i, 71));
          } while (any(or3(diff2(v[0].x, v[0].y, tag16), diff2(v[1].x, v[1].y, tag16), diff2(v[2].x, v[2].y, tag16)) & 0xffffu) && ++it < SPIN_MAX);
#pragma unroll
          for (int i = 0; i < 3; i++) sts(sbase + O_GB + 4 * min(l + 32 * i, 71), __byte_perm(v[i].x, v[i].y, 0x7632));
          __syncwarp();
        }
        wait_cnt<true>(&sc->cnt[C_X + 64], 128 * ep);
        if (elect()) mbar_arrive(full0 + 8 * B_X);
        __syncwarp();
      }
      uint32_t lph = 0;
      auto check_tiles = [&](bool second, int n, int st, uint32_t o1, uint32_t d2nd) {
        const uint32_t b1 = pin(sbase + o1), b2 = pin(sbase + o1 + d2nd);
        int i = 0, it = 0;
#pragma unroll 1
        do {
          const uint32_t so = st * (second ? STAGE2 : STAGE);
          mbar_wait(full0 + 8 * (B_LAND + st), (lph >> st) & 1);
          lph ^= 1u << st;
          uint32_t v[20];
#pragma unroll
          for (int k = 0; k < 20; k++) if (!second || k < 10 || k >= 12) v[k] = lds(k < 12 ? b1 + so + k * 1024 : b2 + so + (k - 12) * 1024); else v[k] = tag1;
#pragma unroll
          for (int k = 0; k < 10; k++) v[k] = diff2(v[2 * k], v[2 * k + 1], tag1);
          const uint32_t bad = or3(or3(or3(v[0], v[1], v[2]), or3(v[3], v[4], v[5]), v[6]), v[7], or3(v[8], v[9], 0));
          if (__builtin_expect(any(bad & 1) && ++it < SPIN_MAX, 0)) {
            FAILCNT(2 + second);
            fence_async_smem();
            __syncwarp();
            if (elect()) load_b(second, i, st);
            __syncwarp();
            continue;
          }
          if (elect()) mbar_arrive(full0 + 8 * st);
          if (++st == NST) st = 0;
          i++;
        } while (i < n);
      };
      if (!sw) check_tiles(false, NV1, 0, a1bytes + l * 32 + (l >> 2) * 4, helper ? 4096 : 12288);
      const bool first = helper || m1 < W0N;
#pragma unroll 1
      for (int k = sw ? first : !first; k <= sw; k++) {
        const uint32_t stg = sbase + (!k ? ST0 * STAGE : helper ? ST1 * STAGE : O_U1);
        const int kbA = (f1 >> 6) + (helper ? 2 : 1) * (k ^ flip), kbB = helper ? (f1 >> 6) + 1 : kbA;
        uint8_t* const uA = upin(sc->u + ((size_t)kbA * D_ + d1) * 128);
        uint8_t* const uB = upin(sc->u + ((size_t)kbB * D_ + (helper ? d1 : d1 + 96)) * 128);
        unsigned* const fA = pin(sc->cnt + C_U + kb2_pos(kbA));
        unsigned* const fB = pin(sc->cnt + C_U + kb2_pos(kbB));
        const bool slow = sw && !helper;
        bar_sync(11 + k, 160);
        if (!slow) { if (elect()) { bulk_st(uA, stg, 96 * 128); TS(k ? 31 : 30); } __syncwarp(); }
        bar_sync(13 + k, 160);
        if (slow) {
          if (g2) mbar_wait(full0 + 8 * B_GO, 0);
          if (first) pause(10 * TRK0);
#pragma unroll 1
          for (int i = 0; i < 20480; i += 2048) {
            if (elect()) bulk_st(uA + i, stg + i, 2048);
            pause(k ? TRKC : TRK0);
          }
        }
        if ((helper ? k : !slow) && elect()) bulk_st(uB, stg + 96 * 128, helper ? 96 * 128 : 64 * 128);
        bulk_commit_wait();
        if (elect()) { red_add(fA, 1); if (helper && k) red_add(fB, 1); }
        if (elect()) {
          if (!k || helper) mbar_arrive(empty0 + 8 * (k ? ST1 : ST0));
          TS(k ? 23 : 17);
          mbar_arrive(full0 + 8 * B_S5);
        }
        __syncwarp();
      }
      if (sw) {
        mbar_wait(full0 + 8 * B_S5, rows);
        if (elect()) { asm volatile("fence.acq_rel.gpu;" ::: "memory"); red_add(&sc->cnt[C_X], 1); }
        __syncwarp();
      }
      if (g2) {
        if (!sw) check_tiles(true, NV2, 3, 16384 + l * 32 + (4 * (g & 1) + (g >> 1)) * 4, 10240);
        else {
          wait_cnt<true>(&sc->cnt[C_X], NCTA * ep);
          if (elect()) {
            mbar_arrive(full0 + 8 * B_X);
            if (cta == 0) sc->cnt[C_EP] = ep;
          }
          __syncwarp();
        }
      }
      __syncwarp();
    } else {
      uint32_t ready = 0;
      int st = 0, ph = 1;
#pragma unroll 1
      for (int kb = 0; kb < 32; kb++) {
        const uint8_t* src = upin(sc->h3 + ((size_t)(kb * 18 + (d1 >> 5)) << 12));
        const uint32_t dst = upin(sbase + st * STAGE + a1bytes), lb = full0 + 8 * ((kb < NV1 ? B_LAND : 0) + st);
        if (kb == NV1) { mbar_wait(full0 + 8 * B_X, 0); fence_async_glb(); ready = ~0u; }
        if (rows && (kb >> 1) == 2) mbar_wait(full0 + 8 * (B_S4 - 4 + kb), 0);
        mbar_wait(empty0 + 8 * st, ph);
        if (elect()) mbar_expect(lb, STAGE - a1bytes);
        wait_flags(sc->cnt + C_H3 + l, (kb & 7) + (kb < 8 * H3G ? 0 : 8), 16 * ep, ready);
        if (elect()) bulk_ld(dst, src, STAGE - a1bytes, lb);
        ring_next<false>(st, ph);
      }
      if (g2) {
        ready = 0;
        st++;
#pragma unroll 1
        for (int i = 0; i < 36; i++) {
          const int kb = kb2_order(i);
          const uint8_t* src = upin(sc->u + ((size_t)(36 * r + kb) * D_ + d2) * 128);
          const uint32_t dst = upin(sbase + st * STAGE2 + 16384), lb = full0 + 8 * ((i < NV2 ? B_LAND : 0) + st);
          if (i == NV2) { mbar_wait(full0 + 8 * B_X, 1); fence_async_glb(); ready = ~0u; }
          mbar_wait(empty0 + 8 * st, ph);
          if (elect()) mbar_expect(lb, 18432);
          wait_flags(sc->cnt + C_U + 64 * r + l, i & 31, 4 * ep, ready);
          if (elect()) {
            bulk_ld(dst, src, 18432, lb);
            if (i == GOAT) mbar_arrive(full0 + 8 * B_GO);
          }
          ring_next<true>(st, ph);
        }
      }
    }
  } else {
    asm volatile("setmaxnreg.inc.sync.aligned.u32 232;");
    const int wgu = wg;
    constexpr uint32_t sb4 = sbase >> 4;
    const int w = wp & 3;
    Ring rg = {0, 0};
    uint32_t* const x1p = p.out + (size_t)(cta + 256 * wp) * 288 + l;
    const uint32_t ad = pin(sbase + (!wg ? ST0 * STAGE : helper ? ST1 * STAGE : O_U1) + (8 * (l >> 4) + (l & 7)) * 128 + (((2 * w + ((l >> 3) & 1)) ^ (l & 7)) << 4));
    const uint32_t uam = pin(g == 2 * t ? 0xfffefffeu : ~0u), uom = tag1 * 0x10001u;
    float acc[96];
    constexpr uint32_t LA = (8192 >> 4) << 16, LB = (4096 >> 4) << 16;
    {
      const int fa = f1 + (helper ? 128 : 64) * (wg ^ flip) + 16 * w + g, fb = helper ? f1 + 64 + 16 * w + g : fa;
      const float a0 = 0.5f * __bfloat162float(p.b1[fa]), a1 = 0.5f * __bfloat162float(p.b1[fa + 8]);
      const float b0 = 0.5f * __bfloat162float(p.b1[fb]), b1 = 0.5f * __bfloat162float(p.b1[fb + 8]);
#pragma unroll
      for (int i = 0; i < 96; i++) acc[i] = i < 48 ? ((i & 2) ? a1 : a0) : ((i & 2) ? b1 : b0);
      reg_fence(acc);
    }
    if (!helper) gemm_main<0>(acc, sb4 + (wgu ^ flip) * 512 + LA, 0, sb4 + 1024 + LB, wgu, rg, rows, x1p, xr);
    else {
      float ac2[96];
#pragma unroll
      for (int i = 0; i < 96; i++) asm volatile("mov.b32 %0, %1;" : "=f"(ac2[i]) : "f"(acc[i]));
      gemm_main<1>(ac2, sb4 + (wgu ^ flip) * 1024 + LA, sb4 + 512 + LA, sb4 + 1536 + LB, wgu, rg, rows, x1p, xr);
#pragma unroll
      for (int i = 0; i < 96; i++) asm volatile("mov.b32 %0, %1;" : "=f"(acc[i]) : "f"(ac2[i]));
    }
    if (t128 == 0) { TS(wg ? 16 : 6); if (wg) TSC(5); }
    {
      float tp[2] = {0.f, 0.f};
#pragma unroll
      for (int j = 0; j < 12; j++) {
        const float* a = &acc[8 * j];
        const float k3 = j < 2 ? GK3 : fmaf(tp[j & 1], 0.0f, GK3);
        float o[8];
#pragma unroll
        for (int e = 0; e < 8; e++) {
          float z = a[e] * fmaf(a[e] * k3, a[e], GK1);
          asm("tanh.approx.f32 %0, %0;" : "+f"(z));
          if (e == GDEP) tp[j & 1] = z;
          o[e] = fmaf(a[e], z, a[e]);
        }
        stmatrix4t(ad + j * 2048, bitsel(pack_bf16(o[0], o[1]), uam, uom), pack_bf16(o[2], o[3]), bitsel(pack_bf16(o[4], o[5]), uam, uom), pack_bf16(o[6], o[7]));
        if (j == 5) {
          fence_async_smem();
          bar_arrive(11 + wgu, 160);
        }
        if ((j == 5 && helper && !wgu) || (j == 9 && !helper)) break;
      }
      fence_async_smem();
      bar_arrive(13 + wgu, 160);
      if (t128 == 0) TS(wg ? 29 : 28);
    }
    if (g2) {
      const int mb = wgu ^ r;
      const int odd = z2 & 1;
      uint4 gq[4];
      uint2 gs;
      {
        float a0 = 0.f, a1 = 0.f;
        if (wgu) { a0 = __bfloat162float(p.b2[s2 + 64 * mb + 16 * w + g]); a1 = __bfloat162float(p.b2[s2 + 64 * mb + 16 * w + 8 + g]); }
#pragma unroll
        for (int i = 0; i < 4; i++) gq[i] = lds4(sbase + O_GB + 32 * odd + 64 * i + 16 * t);
        gs = lds2(sbase + O_GB + (odd ? 0 : 256) + 8 * t);
#pragma unroll
        for (int i = 0; i < 72; i++) acc[i] = (i & 2) ? a1 : a0;
      }
      uint32_t* const ob = p.out + (size_t)(s2 + 64 * mb + 16 * w + g) * 288 + (d2 >> 1);
      uint32_t* const oq = pin(ob + 8 * odd + 4 * t);
      uint32_t* const os = pin(ob + (odd ? 0 : 64) + 2 * t);
      rg.st++;
      gemm_main<3>(acc, sb4 + mb * 512 + LA, 0, sb4 + 1024 + (1 << 16), wgu, rg, rows, x1p, xr);
      if (t128 == 0) { TS(wg ? 20 : 19); if (wg) TSC(22); }
      auto finish = [&](const float* aq, const float* as) {
#pragma unroll
        for (int i = 0; i < 8; i++) {
          const float* a = aq + 16 * (i >> 1) + 2 * (i & 1);
          const uint4 gv = gq[i >> 1];
          red_bf16x8(oq + (i & 1) * 2304 + 16 * (i >> 1), hmul2(gv.x, pack_bf16(a[0], a[1])), hmul2(gv.y, pack_bf16(a[4], a[5])),
                     hmul2(gv.z, pack_bf16(a[8], a[9])), hmul2(gv.w, pack_bf16(a[12], a[13])));
        }
#pragma unroll
        for (int i = 0; i < 2; i++) red_bf16x4(os + i * 2304, hmul2(gs.x, pack_bf16(as[2 * i], as[2 * i + 1])), hmul2(gs.y, pack_bf16(as[2 * i + 4], as[2 * i + 5])));
      };
      if (odd) finish(&acc[8], &acc[0]); else finish(&acc[0], &acc[64]);
      if (t128 == 0) TS(wg ? 7 : 21);
      __syncwarp();
    }
  }
}

typedef CUresult (*EncodeFn)(CUtensorMap*, CUtensorMapDataType, cuuint32_t, void*, const cuuint64_t*, const cuuint64_t*, const cuuint32_t*,
                             const cuuint32_t*, CUtensorMapInterleave, CUtensorMapSwizzle, CUtensorMapL2promotion, CUtensorMapFloatOOBfill);

struct Dim { cuuint64_t n, stride; cuuint32_t box; };
template <int RANK>
void make_map(EncodeFn enc, CUtensorMap* m, bool words, int swz, const void* ptr, const Dim (&d)[RANK]) {
  cuuint64_t gd[RANK], gs[RANK];
  cuuint32_t bx[RANK], es[RANK];
  for (int i = 0; i < RANK; i++) { gd[i] = d[i].n; gs[i] = d[i].stride; bx[i] = d[i].box; es[i] = 1; }
  enc(m, words ? CU_TENSOR_MAP_DATA_TYPE_UINT32 : CU_TENSOR_MAP_DATA_TYPE_BFLOAT16, RANK, const_cast<void*>(ptr), gd, gs + 1, bx, es,
      CU_TENSOR_MAP_INTERLEAVE_NONE, static_cast<CUtensorMapSwizzle>(swz),
      swz == 3 ? CU_TENSOR_MAP_L2_PROMOTION_L2_256B : CU_TENSOR_MAP_L2_PROMOTION_NONE, CU_TENSOR_MAP_FLOAT_OOB_FILL_NONE);
}

}

extern "C" void kernel_launch(void* const* d_in, const int* in_sizes, int n_in, void* d_out, int out_size) {
  (void)in_sizes; (void)n_in; (void)out_size;
  static EncodeFn enc = nullptr;
  static void *sptr = nullptr, *tptr = nullptr;
  if (!enc) {
    void* f = nullptr; cudaDriverEntryPointQueryResult qr;
    cudaGetDriverEntryPoint("cuTensorMapEncodeTiled", &f, cudaEnableDefault, &qr);
    enc = reinterpret_cast<EncodeFn>(f);
    cudaFuncSetAttribute(fused_kernel, cudaFuncAttributeMaxDynamicSharedMemorySize, SMEM_BYTES);
    cudaGetSymbolAddress(&sptr, g_s);
    cudaGetSymbolAddress(&tptr, T_TAB);
  }
  Params p;
  p.x = (const __nv_bfloat16*)d_in[0]; p.wr = (const __nv_bfloat16*)d_in[1]; p.wi = (const __nv_bfloat16*)d_in[2];
  p.b1 = (const __nv_bfloat16*)d_in[5]; p.b2 = (const __nv_bfloat16*)d_in[7];
  p.c = (const __nv_bfloat16*)d_in[8]; p.wmod = (const __nv_bfloat16*)d_in[9];
  p.w1 = (const __nv_bfloat16*)d_in[4]; p.w2 = (const __nv_bfloat16*)d_in[6];
  p.out = static_cast<uint32_t*>(d_out); p.s = static_cast<Scratch*>(sptr); p.tab = static_cast<const uint4*>(tptr);
  Maps maps;
  make_map<4>(enc, &maps.w1a, false, 3, p.w1, {{64, 0, 64}, {16, 128 * 2 * F_, 4}, {128, 2 * F_, 16}, {72, 128, 2}});
  make_map<4>(enc, &maps.w1b, false, 3, p.w1, {{64, 0, 64}, {16, 128 * 2 * F_, 4}, {128, 2 * F_, 16}, {72, 128, 3}});
  make_map<3>(enc, &maps.w2, false, 3, p.w2, {{64, 0, 64}, {F_, 2 * S_, 64}, {32, 128, 2}});
  make_map<2>(enc, &maps.z1, true, 0, p.s->z1, {{5120, 0, 40}, {120, 20480, 60}});
  for (int i = 0; i < 2; i++) make_map<2>(enc, &maps.z2[i], true, 0, p.s->z2, {{4800, 0, i ? 16u : 24u}, {128, 19200, 128}});
  for (int i = 0; i < 4; i++) make_map<2>(enc, &maps.wf[i], false, 2 - (i & 1), (i & 2) ? p.wi : p.wr, {{16 * DF_, 0, (i & 1) ? 16u : 32u}, {128, 32 * DF_, 128}});
  make_map<2>(enc, &maps.wm, false, 1, p.wmod, {{6 * D_, 0, 16}, {D_, 12 * D_, 192}});
  for (int i = 0; i < 2; i++) make_map<3>(enc, &maps.h3[i], true, 0, p.s->h3, {{1024, 0, 64}, {144, 4096, 18}, {4, 144 * 4096, i ? 4u - H3G : H3G}});
  fused_kernel<<<NCTA, NTHR, SMEM_BYTES, cudaStreamPerThread>>>(p, maps);
}
```

```cpp
#include <cuda_runtime.h>
#include <cuda_bf16.h>
#include <cuda.h>
#include <stdint.h>

namespace {

constexpr int S_ = 2048, D_ = 576, DF_ = 289, F_ = 4608;
constexpr int NCTA = 132, NTHR = 384;
constexpr int STAGE = 36864, NST = 6;
constexpr int STAGE2 = 34816, O_U1 = NST * STAGE2, O_GB = O_U1 + 20480, SMEM_BYTES = 232448;
constexpr uint32_t sbase = 1024, red = sbase + NST * STAGE, full0 = sbase + SMEM_BYTES - 256, empty0 = full0 + 8 * NST;
constexpr int O_NRM = 0, O_B1 = 19456, O_Z1 = 38912, O_P2 = 59392, O_ST = 3 * STAGE;
constexpr int O_RAW = 4 * STAGE;
constexpr int O_IN = 4 * STAGE, O_Y = O_IN + 19456, O_B3 = O_IN + 38912, O_MOD = O_IN + 57344;

__device__ __align__(128) const uint32_t T_TAB[5632] = {
0x3f803f80,0xbf803f80,0x3f803f80,0xbf803f80,0x3f803f80,0xbf803f80,0x3f803f80,0xbf803f80,0x3f803f80,0xbf803f80,0x3f803f80,0xbf803f80,
0x3f803f80,0xbf803f80,0x3f803f80,0xbf803f80,0x3f7f3f80,0xbdc90000,0x3f223f35,0xbf46bf35,0x3f753f7b,0xbe95be48,0x3ef13f0e,0xbf62bf55,
0x3f623f6d,0xbef1bec4,0x3e953ec4,0xbf75bf6d,0x3f463f55,0xbf22bf0e,0x3dc93e48,0xbf7fbf7b,0x3f7b3f80,0xbe480000,0xbe480000,0xbf7bbf80,
0x3f553f6d,0xbf0ebec4,0xbf0ebec4,0xbf55bf6d,0x3f0e3f35,0xbf55bf35,0xbf55bf35,0xbf0ebf35,0x3e483ec4,0xbf7bbf6d,0xbf7bbf6d,0xbe48bec4,
0x3f753f80,0xbe950000,0xbf62bf35,0xbef1bf35,0x3f223f55,0xbf46bf0e,0xbf7fbf7b,0x3dc9be48,0x3dc93ec4,0xbf7fbf6d,0xbf46bf6d,0x3f223ec4,
0xbef1be48,0xbf62bf7b,0xbe95bf0e,0x3f753f55,0x3f6d3f80,0xbec40000,0xbf6dbf80,0x3ec40000,0x3ec43f35,0xbf6dbf35,0xbec4bf35,0x3f6d3f35,
0xbec40000,0xbf6dbf80,0x3ec40000,0x3f6d3f80,0xbf6dbf35,0xbec4bf35,0x3f6d3f35,0x3ec43f35,0x3f623f80,0xbef10000,0xbe95bf35,0x3f753f35,
0x3dc93f0e,0xbf7fbf55,0x3f223e48,0x3f463f7b,0xbf46bec4,0xbf22bf6d,0x3f7f3f6d,0xbdc93ec4,0xbf75bf7b,0x3e95be48,0x3ef13f55,0xbf62bf0e,
0x3f553f80,0xbf0e0000,0x3f0e0000,0x3f553f80,0xbe483ec4,0xbf7bbf6d,0x3f7b3f6d,0xbe483ec4,0xbf7bbf35,0xbe48bf35,0x3e483f35,0xbf7bbf35,
0xbf0ebf6d,0x3f553ec4,0xbf55bec4,0xbf0ebf6d,0x3f463f80,0xbf220000,0x3f7f3f35,0x3dc93f35,0xbef13e48,0xbf62bf7b,0x3e953f55,0xbf75bf0e,
0xbf75bf6d,0x3e95bec4,0xbf62bec4,0xbef1bf6d,0x3dc9bf0e,0x3f7f3f55,0xbf22bf7b,0x3f463e48,0x3f353f80,0xbf350000,0x3f353f80,0xbf350000,
0xbf350000,0xbf35bf80,0xbf350000,0xbf35bf80,0xbf35bf80,0x3f350000,0xbf35bf80,0x3f350000,0x3f350000,0x3f353f80,0x3f350000,0x3f353f80,
0x3f223f80,0xbf460000,0xbdc93f35,0xbf7fbf35,0xbf62be48,0xbef1bf7b,0xbf75bf55,0x3e95bf0e,0xbe95bf6d,0x3f753ec4,0x3ef1bec4,0x3f623f6d,
0x3f7f3f0e,0x3dc93f55,0x3f463f7b,0xbf223e48,0x3f0e3f80,0xbf550000,0xbf550000,0xbf0ebf80,0xbf7bbec4,0xbe48bf6d,0xbe48bf6d,0x3f7b3ec4,
0x3e48bf35,0x3f7b3f35,0x3f7b3f35,0xbe483f35,0x3f553f6d,0xbf0e3ec4,0xbf0e3ec4,0xbf55bf6d,0x3ef13f80,0xbf620000,0xbf75bf35,0x3e95bf35,
0xbf7fbf0e,0x3dc9bf55,0x3f46be48,0x3f223f7b,0x3f22bec4,0x3f463f6d,0x3dc93f6d,0xbf7fbec4,0x3e953f7b,0xbf75be48,0xbf62bf55,0x3ef1bf0e,
0x3ec43f80,0xbf6d0000,0xbec4bf80,0x3f6d0000,0xbf6dbf35,0x3ec4bf35,0x3f6d3f35,0xbec43f35,0x3f6d0000,0x3ec43f80,0xbf6d0000,0xbec4bf80,
0xbec43f35,0xbf6dbf35,0x3ec4bf35,0x3f6d3f35,0x3e953f80,0xbf750000,0x3ef1bf35,0x3f623f35,0xbf46bf55,0x3f22bf0e,0x3dc93f7b,0xbf7fbe48,
0x3f7f3ec4,0xbdc93f6d,0xbf22bf6d,0x3f46bec4,0xbf623e48,0xbef1bf7b,0x3f753f0e,0xbe953f55,0x3e483f80,0xbf7b0000,0x3f7b0000,0x3e483f80,
0xbf0ebf6d,0x3f55bec4,0xbf553ec4,0xbf0ebf6d,0x3f553f35,0xbf0e3f35,0x3f0ebf35,0x3f553f35,0xbf7bbec4,0x3e48bf6d,0xbe483f6d,0xbf7bbec4,
0x3dc93f80,0xbf7f0000,0x3f463f35,0xbf223f35,0xbe95bf7b,0x3f75be48,0xbf62bf0e,0x3ef1bf55,0x3ef13f6d,0xbf623ec4,0x3f753ec4,0xbe953f6d,
0xbf22bf55,0x3f46bf0e,0xbf7fbe48,0x3dc9bf7b,0x3f80,0xbf800000,0x3f80,0xbf800000,0xbf80,0x3f800000,0xbf80,0x3f800000,
0x3f80,0xbf800000,0x3f80,0xbf800000,0xbf80,0x3f800000,0xbf80,0x3f800000,0xbdc93f80,0xbf7f0000,0xbf463f35,0xbf22bf35,
0x3e95bf7b,0x3f753e48,0x3f62bf0e,0x3ef13f55,0xbef13f6d,0xbf62bec4,0xbf753ec4,0xbe95bf6d,0x3f22bf55,0x3f463f0e,0x3f7fbe48,0x3dc93f7b,
0xbe483f80,0xbf7b0000,0xbf7b0000,0x3e48bf80,0x3f0ebf6d,0x3f553ec4,0x3f553ec4,0xbf0e3f6d,0xbf553f35,0xbf0ebf35,0xbf0ebf35,0x3f55bf35,
0x3f7bbec4,0x3e483f6d,0x3e483f6d,0xbf7b3ec4,0xbe953f80,0xbf750000,0xbef1bf35,0x3f62bf35,0x3f46bf55,0x3f223f0e,0xbdc93f7b,0xbf7f3e48,
0xbf7f3ec4,0xbdc9bf6d,0x3f22bf6d,0x3f463ec4,0x3f623e48,0xbef13f7b,0xbf753f0e,0xbe95bf55,0xbec43f80,0xbf6d0000,0x3ec4bf80,0x3f6d0000,
0x3f6dbf35,0x3ec43f35,0xbf6d3f35,0xbec4bf35,0xbf6d0000,0x3ec4bf80,0x3f6d0000,0xbec43f80,0x3ec43f35,0xbf6d3f35,0xbec4bf35,0x3f6dbf35,
0xbef13f80,0xbf620000,0x3f75bf35,0x3e953f35,0x3f7fbf0e,0x3dc93f55,0xbf46be48,0x3f22bf7b,0xbf22bec4,0x3f46bf6d,0xbdc93f6d,0xbf7f3ec4,
0xbe953f7b,0xbf753e48,0x3f62bf55,0x3ef13f0e,0xbf0e3f80,0xbf550000,0x3f550000,0xbf0e3f80,0x3f7bbec4,0xbe483f6d,0x3e48bf6d,0x3f7bbec4,
0xbe48bf35,0x3f7bbf35,0xbf7b3f35,0xbe48bf35,0xbf553f6d,0xbf0ebec4,0x3f0e3ec4,0xbf553f6d,0xbf223f80,0xbf460000,0x3dc93f35,0xbf7f3f35,
0x3f62be48,0xbef13f7b,0x3f75bf55,0x3e953f0e,0x3e95bf6d,0x3f75bec4,0xbef1bec4,0x3f62bf6d,0xbf7f3f0e,0x3dc9bf55,0xbf463f7b,0xbf22be48,
0xbf353f80,0xbf350000,0xbf353f80,0xbf350000,0x3f350000,0xbf353f80,0x3f350000,0xbf353f80,0x3f35bf80,0x3f350000,0x3f35bf80,0x3f350000,
0xbf350000,0x3f35bf80,0xbf350000,0x3f35bf80,0xbf463f80,0xbf220000,0xbf7f3f35,0x3dc9bf35,0x3ef13e48,0xbf623f7b,0xbe953f55,0xbf753f0e,
0x3f75bf6d,0x3e953ec4,0x3f62bec4,0xbef13f6d,0xbdc9bf0e,0x3f7fbf55,0x3f22bf7b,0x3f46be48,0xbf553f80,0xbf0e0000,0xbf0e0000,0x3f55bf80,
0x3e483ec4,0xbf7b3f6d,0xbf7b3f6d,0xbe48bec4,0x3f7bbf35,0xbe483f35,0xbe483f35,0xbf7b3f35,0x3f0ebf6d,0x3f55bec4,0x3f55bec4,0xbf0e3f6d,
0xbf623f80,0xbef10000,0x3e95bf35,0x3f75bf35,0xbdc93f0e,0xbf7f3f55,0xbf223e48,0x3f46bf7b,0x3f46bec4,0xbf223f6d,0xbf7f3f6d,0xbdc9bec4,
0x3f75bf7b,0x3e953e48,0xbef13f55,0xbf623f0e,0xbf6d3f80,0xbec40000,0x3f6dbf80,0x3ec40000,0xbec43f35,0xbf6d3f35,0x3ec4bf35,0x3f6dbf35,
0x3ec40000,0xbf6d3f80,0xbec40000,0x3f6dbf80,0x3f6dbf35,0xbec43f35,0xbf6d3f35,0x3ec4bf35,0xbf753f80,0xbe950000,0x3f62bf35,0xbef13f35,
0xbf223f55,0xbf463f0e,0x3f7fbf7b,0x3dc93e48,0xbdc93ec4,0xbf7f3f6d,0x3f46bf6d,0x3f22bec4,0x3ef1be48,0xbf623f7b,0x3e95bf0e,0x3f75bf55,
0xbf7b3f80,0xbe480000,0x3e480000,0xbf7b3f80,0xbf553f6d,0xbf0e3ec4,0x3f0ebec4,0xbf553f6d,0xbf0e3f35,0xbf553f35,0x3f55bf35,0xbf0e3f35,
0xbe483ec4,0xbf7b3f6d,0x3f7bbf6d,0xbe483ec4,0xbf7f3f80,0xbdc90000,0xbf223f35,0xbf463f35,0xbf753f7b,0xbe953e48,0xbef13f0e,0xbf623f55,
0xbf623f6d,0xbef13ec4,0xbe953ec4,0xbf753f6d,0xbf463f55,0xbf223f0e,0xbdc93e48,0xbf7f3f7b,0x3f803f80,0xbf803f80,0x3f803f80,0xbf803f80,
0x3f803f80,0xbf803f80,0x3f803f80,0xbf803f80,0x3f803f80,0xbf803f80,0x3f803f80,0xbf803f80,0x3f803f80,0xbf803f80,0x3f803f80,0xbf803f80,
0xbdc90000,0xbf7fbf80,0xbf46bf35,0xbf22bf35,0xbe95be48,0xbf75bf7b,0xbf62bf55,0xbef1bf0e,0xbef1bec4,0xbf62bf6d,0xbf75bf6d,0xbe95bec4,
0xbf22bf0e,0xbf46bf55,0xbf7fbf7b,0xbdc9be48,0xbf7bbf80,0x3e480000,0x3e480000,0x3f7b3f80,0xbf55bf6d,0x3f0e3ec4,0x3f0e3ec4,0x3f553f6d,
0xbf0ebf35,0x3f553f35,0x3f553f35,0x3f0e3f35,0xbe48bec4,0x3f7b3f6d,0x3f7b3f6d,0x3e483ec4,0x3e950000,0x3f753f80,0x3ef13f35,0xbf62bf35,
0x3f463f0e,0x3f223f55,0xbdc93e48,0xbf7fbf7b,0x3f7f3f6d,0x3dc93ec4,0xbf22bec4,0xbf46bf6d,0x3f623f7b,0xbef1be48,0xbf75bf55,0xbe95bf0e,
0x3f6d3f80,0xbec40000,0xbf6dbf80,0x3ec40000,0x3ec43f35,0xbf6dbf35,0xbec4bf35,0x3f6d3f35,0xbec40000,0xbf6dbf80,0x3ec40000,0x3f6d3f80,
0xbf6dbf35,0xbec4bf35,0x3f6d3f35,0x3ec43f35,0xbef10000,0xbf62bf80,0x3f753f35,0x3e953f35,0xbf7fbf55,0xbdc9bf0e,0x3f463f7b,0xbf22be48,
0xbf22bf6d,0x3f463ec4,0xbdc93ec4,0xbf7fbf6d,0x3e95be48,0x3f753f7b,0xbf62bf0e,0xbef1bf55,0xbf55bf80,0x3f0e0000,0xbf0e0000,0xbf55bf80,
0x3e48bec4,0x3f7b3f6d,0xbf7bbf6d,0x3e48bec4,0x3f7b3f35,0x3e483f35,0xbe48bf35,0x3f7b3f35,0x3f0e3f6d,0xbf55bec4,0x3f553ec4,0x3f0e3f6d,
0x3f220000,0x3f463f80,0xbdc9bf35,0x3f7f3f35,0x3f623f7b,0xbef13e48,0x3f753f0e,0x3e953f55,0xbe953ec4,0xbf75bf6d,0x3ef13f6d,0xbf62bec4,
0xbf7fbf55,0x3dc9bf0e,0xbf46be48,0xbf22bf7b,0x3f353f80,0xbf350000,0x3f353f80,0xbf350000,0xbf350000,0xbf35bf80,0xbf350000,0xbf35bf80,
0xbf35bf80,0x3f350000,0xbf35bf80,0x3f350000,0x3f350000,0x3f353f80,0x3f350000,0x3f353f80,0xbf460000,0xbf22bf80,0xbf7fbf35,0x3dc9bf35,
0xbef1bf7b,0x3f623e48,0x3e95bf0e,0x3f753f55,0x3f753ec4,0x3e953f6d,0x3f623f6d,0xbef13ec4,0x3dc93f55,0xbf7fbf0e,0xbf223e48,0xbf46bf7b,
0xbf0ebf80,0x3f550000,0x3f550000,0x3f0e3f80,0x3f7b3ec4,0x3e483f6d,0x3e483f6d,0xbf7bbec4,0xbe483f35,0xbf7bbf35,0xbf7bbf35,0x3e48bf35,
0xbf55bf6d,0x3f0ebec4,0x3f0ebec4,0x3f553f6d,0x3f620000,0x3ef13f80,0xbe953f35,0xbf75bf35,0xbdc93f55,0xbf7fbf0e,0xbf22bf7b,0x3f46be48,
0xbf46bf6d,0x3f22bec4,0x3f7f3ec4,0x3dc93f6d,0x3f753e48,0x3e953f7b,0xbef13f0e,0xbf62bf55,0x3ec43f80,0xbf6d0000,0xbec4bf80,0x3f6d0000,
0xbf6dbf35,0x3ec4bf35,0x3f6d3f35,0xbec43f35,0x3f6d0000,0x3ec43f80,0xbf6d0000,0xbec4bf80,0xbec43f35,0xbf6dbf35,0x3ec4bf35,0x3f6d3f35,
0xbf750000,0xbe95bf80,0x3f623f35,0xbef13f35,0x3f22bf0e,0x3f463f55,0xbf7fbe48,0xbdc9bf7b,0xbdc93f6d,0xbf7fbec4,0x3f46bec4,0x3f223f6d,
0xbef1bf7b,0x3f62be48,0xbe953f55,0xbf75bf0e,0xbe48bf80,0x3f7b0000,0xbf7b0000,0xbe48bf80,0x3f0e3f6d,0xbf553ec4,0x3f55bec4,0x3f0e3f6d,
0xbf55bf35,0x3f0ebf35,0xbf0e3f35,0xbf55bf35,0x3f7b3ec4,0xbe483f6d,0x3e48bf6d,0x3f7b3ec4,0x3f7f0000,0x3dc93f80,0x3f22bf35,0x3f463f35,
0xbf753e48,0xbe95bf7b,0xbef13f55,0xbf62bf0e,0x3f62bec4,0x3ef13f6d,0x3e95bf6d,0x3f753ec4,0xbf463f0e,0xbf22bf55,0xbdc93f7b,0xbf7fbe48,
0x3f80,0xbf800000,0x3f80,0xbf800000,0xbf80,0x3f800000,0xbf80,0x3f800000,0x3f80,0xbf800000,0x3f80,0xbf800000,
0xbf80,0x3f800000,0xbf80,0x3f800000,0xbf7f0000,0x3dc9bf80,0xbf22bf35,0x3f46bf35,0x3f753e48,0xbe953f7b,0x3ef13f55,0xbf623f0e,
0xbf62bec4,0x3ef1bf6d,0xbe95bf6d,0x3f75bec4,0x3f463f0e,0xbf223f55,0x3dc93f7b,0xbf7f3e48,0x3e48bf80,0x3f7b0000,0x3f7b0000,0xbe483f80,
0xbf0e3f6d,0xbf55bec4,0xbf55bec4,0x3f0ebf6d,0x3f55bf35,0x3f0e3f35,0x3f0e3f35,0xbf553f35,0xbf7b3ec4,0xbe48bf6d,0xbe48bf6d,0x3f7bbec4,
0x3f750000,0xbe953f80,0xbf623f35,0xbef1bf35,0xbf22bf0e,0x3f46bf55,0x3f7fbe48,0xbdc93f7b,0x3dc93f6d,0xbf7f3ec4,0xbf46bec4,0x3f22bf6d,
0x3ef1bf7b,0x3f623e48,0x3e953f55,0xbf753f0e,0xbec43f80,0xbf6d0000,0x3ec4bf80,0x3f6d0000,0x3f6dbf35,0x3ec43f35,0xbf6d3f35,0xbec4bf35,
0xbf6d0000,0x3ec4bf80,0x3f6d0000,0xbec43f80,0x3ec43f35,0xbf6d3f35,0xbec4bf35,0x3f6dbf35,0xbf620000,0x3ef1bf80,0x3e953f35,0xbf753f35,
0x3dc93f55,0xbf7f3f0e,0x3f22bf7b,0x3f463e48,0x3f46bf6d,0x3f223ec4,0xbf7f3ec4,0x3dc9bf6d,0xbf753e48,0x3e95bf7b,0x3ef13f0e,0xbf623f55,
0x3f0ebf80,0x3f550000,0xbf550000,0x3f0ebf80,0xbf7b3ec4,0x3e48bf6d,0xbe483f6d,0xbf7b3ec4,0x3e483f35,0xbf7b3f35,0x3f7bbf35,0x3e483f35,
0x3f55bf6d,0x3f0e3ec4,0xbf0ebec4,0x3f55bf6d,0x3f460000,0xbf223f80,0x3f7fbf35,0x3dc93f35,0x3ef1bf7b,0x3f62be48,0xbe95bf0e,0x3f75bf55,
0xbf753ec4,0x3e95bf6d,0xbf623f6d,0xbef1bec4,0xbdc93f55,0xbf7f3f0e,0x3f223e48,0xbf463f7b,0xbf353f80,0xbf350000,0xbf353f80,0xbf350000,
0x3f350000,0xbf353f80,0x3f350000,0xbf353f80,0x3f35bf80,0x3f350000,0x3f35bf80,0x3f350000,0xbf350000,0x3f35bf80,0xbf350000,0x3f35bf80,
0xbf220000,0x3f46bf80,0x3dc9bf35,0x3f7fbf35,0xbf623f7b,0xbef1be48,0xbf753f0e,0x3e95bf55,0x3e953ec4,0xbf753f6d,0xbef13f6d,0xbf623ec4,
0x3f7fbf55,0x3dc93f0e,0x3f46be48,0xbf223f7b,0x3f55bf80,0x3f0e0000,0x3f0e0000,0xbf553f80,0xbe48bec4,0x3f7bbf6d,0x3f7bbf6d,0x3e483ec4,
0xbf7b3f35,0x3e48bf35,0x3e48bf35,0x3f7bbf35,0xbf0e3f6d,0xbf553ec4,0xbf553ec4,0x3f0ebf6d,0x3ef10000,0xbf623f80,0xbf753f35,0x3e95bf35,
0x3f7fbf55,0xbdc93f0e,0xbf463f7b,0xbf223e48,0x3f22bf6d,0x3f46bec4,0x3dc93ec4,0xbf7f3f6d,0xbe95be48,0x3f75bf7b,0x3f62bf0e,0xbef13f55,
0xbf6d3f80,0xbec40000,0x3f6dbf80,0x3ec40000,0xbec43f35,0xbf6d3f35,0x3ec4bf35,0x3f6dbf35,0x3ec40000,0xbf6d3f80,0xbec40000,0x3f6dbf80,
0x3f6dbf35,0xbec43f35,0xbf6d3f35,0x3ec4bf35,0xbe950000,0x3f75bf80,0xbef13f35,0xbf623f35,0xbf463f0e,0x3f22bf55,0x3dc93e48,0xbf7f3f7b,
0xbf7f3f6d,0x3dc9bec4,0x3f22bec4,0xbf463f6d,0xbf623f7b,0xbef13e48,0x3f75bf55,0xbe953f0e,0x3f7bbf80,0x3e480000,0xbe480000,0x3f7bbf80,
0x3f55bf6d,0x3f0ebec4,0xbf0e3ec4,0x3f55bf6d,0x3f0ebf35,0x3f55bf35,0xbf553f35,0x3f0ebf35,0x3e48bec4,0x3f7bbf6d,0xbf7b3f6d,0x3e48bec4,
0x3dc90000,0xbf7f3f80,0x3f46bf35,0xbf223f35,0x3e95be48,0xbf753f7b,0x3f62bf55,0xbef13f0e,0x3ef1bec4,0xbf623f6d,0x3f75bf6d,0xbe953ec4,
0x3f22bf0e,0xbf463f55,0x3f7fbf7b,0xbdc93e48,0x3f803f80,0xbf803f80,0x3f803f80,0xbf803f80,0x3f803f80,0xbf803f80,0x3f803f80,0xbf803f80,
0x3f803f80,0xbf803f80,0x3f803f80,0xbf803f80,0x3f803f80,0xbf803f80,0x3f803f80,0xbf803f80,0xbf7fbf80,0x3dc90000,0xbf22bf35,0x3f463f35,
0xbf75bf7b,0x3e953e48,0xbef1bf0e,0x3f623f55,0xbf62bf6d,0x3ef13ec4,0xbe95bec4,0x3f753f6d,0xbf46bf55,0x3f223f0e,0xbdc9be48,0x3f7f3f7b,
0x3f7b3f80,0xbe480000,0xbe480000,0xbf7bbf80,0x3f553f6d,0xbf0ebec4,0xbf0ebec4,0xbf55bf6d,0x3f0e3f35,0xbf55bf35,0xbf55bf35,0xbf0ebf35,
0x3e483ec4,0xbf7bbf6d,0xbf7bbf6d,0xbe48bec4,0xbf75bf80,0x3e950000,0x3f623f35,0x3ef13f35,0xbf22bf55,0x3f463f0e,0x3f7f3f7b,0xbdc93e48,
0xbdc9bec4,0x3f7f3f6d,0x3f463f6d,0xbf22bec4,0x3ef13e48,0x3f623f7b,0x3e953f0e,0xbf75bf55,0x3f6d3f80,0xbec40000,0xbf6dbf80,0x3ec40000,
0x3ec43f35,0xbf6dbf35,0xbec4bf35,0x3f6d3f35,0xbec40000,0xbf6dbf80,0x3ec40000,0x3f6d3f80,0xbf6dbf35,0xbec4bf35,0x3f6d3f35,0x3ec43f35,
0xbf62bf80,0x3ef10000,0x3e953f35,0xbf75bf35,0xbdc9bf0e,0x3f7f3f55,0xbf22be48,0xbf46bf7b,0x3f463ec4,0x3f223f6d,0xbf7fbf6d,0x3dc9bec4,
0x3f753f7b,0xbe953e48,0xbef1bf55,0x3f623f0e,0x3f553f80,0xbf0e0000,0x3f0e0000,0x3f553f80,0xbe483ec4,0xbf7bbf6d,0x3f7b3f6d,0xbe483ec4,
0xbf7bbf35,0xbe48bf35,0x3e483f35,0xbf7bbf35,0xbf0ebf6d,0x3f553ec4,0xbf55bec4,0xbf0ebf6d,0xbf46bf80,0x3f220000,0xbf7fbf35,0xbdc9bf35,
0x3ef1be48,0x3f623f7b,0xbe95bf55,0x3f753f0e,0x3f753f6d,0xbe953ec4,0x3f623ec4,0x3ef13f6d,0xbdc93f0e,0xbf7fbf55,0x3f223f7b,0xbf46be48,
0x3f353f80,0xbf350000,0x3f353f80,0xbf350000,0xbf350000,0xbf35bf80,0xbf350000,0xbf35bf80,0xbf35bf80,0x3f350000,0xbf35bf80,0x3f350000,
0x3f350000,0x3f353f80,0x3f350000,0x3f353f80,0xbf22bf80,0x3f460000,0x3dc9bf35,0x3f7f3f35,0x3f623e48,0x3ef13f7b,0x3f753f55,0xbe953f0e,
0x3e953f6d,0xbf75bec4,0xbef13ec4,0xbf62bf6d,0xbf7fbf0e,0xbdc9bf55,0xbf46bf7b,0x3f22be48,0x3f0e3f80,0xbf550000,0xbf550000,0xbf0ebf80,
0xbf7bbec4,0xbe48bf6d,0xbe48bf6d,0x3f7b3ec4,0x3e48bf35,0x3f7b3f35,0x3f7b3f35,0xbe483f35,0x3f553f6d,0xbf0e3ec4,0xbf0e3ec4,0xbf55bf6d,
0xbef1bf80,0x3f620000,0x3f753f35,0xbe953f35,0x3f7f3f0e,0xbdc93f55,0xbf463e48,0xbf22bf7b,0xbf223ec4,0xbf46bf6d,0xbdc9bf6d,0x3f7f3ec4,
0xbe95bf7b,0x3f753e48,0x3f623f55,0xbef13f0e,0x3ec43f80,0xbf6d0000,0xbec4bf80,0x3f6d0000,0xbf6dbf35,0x3ec4bf35,0x3f6d3f35,0xbec43f35,
0x3f6d0000,0x3ec43f80,0xbf6d0000,0xbec4bf80,0xbec43f35,0xbf6dbf35,0x3ec4bf35,0x3f6d3f35,0xbe95bf80,0x3f750000,0xbef13f35,0xbf62bf35,
0x3f463f55,0xbf223f0e,0xbdc9bf7b,0x3f7f3e48,0xbf7fbec4,0x3dc9bf6d,0x3f223f6d,0xbf463ec4,0x3f62be48,0x3ef13f7b,0xbf75bf0e,0x3e95bf55,
0x3e483f80,0xbf7b0000,0x3f7b0000,0x3e483f80,0xbf0ebf6d,0x3f55bec4,0xbf553ec4,0xbf0ebf6d,0x3f553f35,0xbf0e3f35,0x3f0ebf35,0x3f553f35,
0xbf7bbec4,0x3e48bf6d,0xbe483f6d,0xbf7bbec4,0xbdc9bf80,0x3f7f0000,0xbf46bf35,0x3f22bf35,0x3e953f7b,0xbf753e48,0x3f623f0e,0xbef13f55,
0xbef1bf6d,0x3f62bec4,0xbf75bec4,0x3e95bf6d,0x3f223f55,0xbf463f0e,0x3f7f3e48,0xbdc93f7b,0x3f80,0xbf800000,0x3f80,0xbf800000,
0xbf80,0x3f800000,0xbf80,0x3f800000,0x3f80,0xbf800000,0x3f80,0xbf800000,0xbf80,0x3f800000,0xbf80,0x3f800000,
0x3dc9bf80,0x3f7f0000,0x3f46bf35,0x3f223f35,0xbe953f7b,0xbf75be48,0xbf623f0e,0xbef1bf55,0x3ef1bf6d,0x3f623ec4,0x3f75bec4,0x3e953f6d,
0xbf223f55,0xbf46bf0e,0xbf7f3e48,0xbdc9bf7b,0xbe483f80,0xbf7b0000,0xbf7b0000,0x3e48bf80,0x3f0ebf6d,0x3f553ec4,0x3f553ec4,0xbf0e3f6d,
0xbf553f35,0xbf0ebf35,0xbf0ebf35,0x3f55bf35,0x3f7bbec4,0x3e483f6d,0x3e483f6d,0xbf7b3ec4,0x3e95bf80,0x3f750000,0x3ef13f35,0xbf623f35,
0xbf463f55,0xbf22bf0e,0x3dc9bf7b,0x3f7fbe48,0x3f7fbec4,0x3dc93f6d,0xbf223f6d,0xbf46bec4,0xbf62be48,0x3ef1bf7b,0x3f75bf0e,0x3e953f55,
0xbec43f80,0xbf6d0000,0x3ec4bf80,0x3f6d0000,0x3f6dbf35,0x3ec43f35,0xbf6d3f35,0xbec4bf35,0xbf6d0000,0x3ec4bf80,0x3f6d0000,0xbec43f80,
0x3ec43f35,0xbf6d3f35,0xbec4bf35,0x3f6dbf35,0x3ef1bf80,0x3f620000,0xbf753f35,0xbe95bf35,0xbf7f3f0e,0xbdc9bf55,0x3f463e48,0xbf223f7b,
0x3f223ec4,0xbf463f6d,0x3dc9bf6d,0x3f7fbec4,0x3e95bf7b,0x3f75be48,0xbf623f55,0xbef1bf0e,0xbf0e3f80,0xbf550000,0x3f550000,0xbf0e3f80,
0x3f7bbec4,0xbe483f6d,0x3e48bf6d,0x3f7bbec4,0xbe48bf35,0x3f7bbf35,0xbf7b3f35,0xbe48bf35,0xbf553f6d,0xbf0ebec4,0x3f0e3ec4,0xbf553f6d,
0x3f22bf80,0x3f460000,0xbdc9bf35,0x3f7fbf35,0xbf623e48,0x3ef1bf7b,0xbf753f55,0xbe95bf0e,0xbe953f6d,0xbf753ec4,0x3ef13ec4,0xbf623f6d,
0x3f7fbf0e,0xbdc93f55,0x3f46bf7b,0x3f223e48,0xbf353f80,0xbf350000,0xbf353f80,0xbf350000,0x3f350000,0xbf353f80,0x3f350000,0xbf353f80,
0x3f35bf80,0x3f350000,0x3f35bf80,0x3f350000,0xbf350000,0x3f35bf80,0xbf350000,0x3f35bf80,0x3f46bf80,0x3f220000,0x3f7fbf35,0xbdc93f35,
0xbef1be48,0x3f62bf7b,0x3e95bf55,0x3f75bf0e,0xbf753f6d,0xbe95bec4,0xbf623ec4,0x3ef1bf6d,0x3dc93f0e,0xbf7f3f55,0xbf223f7b,0xbf463e48,
0xbf553f80,0xbf0e0000,0xbf0e0000,0x3f55bf80,0x3e483ec4,0xbf7b3f6d,0xbf7b3f6d,0xbe48bec4,0x3f7bbf35,0xbe483f35,0xbe483f35,0xbf7b3f35,
0x3f0ebf6d,0x3f55bec4,0x3f55bec4,0xbf0e3f6d,0x3f62bf80,0x3ef10000,0xbe953f35,0xbf753f35,0x3dc9bf0e,0x3f7fbf55,0x3f22be48,0xbf463f7b,
0xbf463ec4,0x3f22bf6d,0x3f7fbf6d,0x3dc93ec4,0xbf753f7b,0xbe95be48,0x3ef1bf55,0x3f62bf0e,0xbf6d3f80,0xbec40000,0x3f6dbf80,0x3ec40000,
0xbec43f35,0xbf6d3f35,0x3ec4bf35,0x3f6dbf35,0x3ec40000,0xbf6d3f80,0xbec40000,0x3f6dbf80,0x3f6dbf35,0xbec43f35,0xbf6d3f35,0x3ec4bf35,
0x3f75bf80,0x3e950000,0xbf623f35,0x3ef1bf35,0x3f22bf55,0x3f46bf0e,0xbf7f3f7b,0xbdc9be48,0x3dc9bec4,0x3f7fbf6d,0xbf463f6d,0xbf223ec4,
0xbef13e48,0x3f62bf7b,0xbe953f0e,0xbf753f55,0xbf7b3f80,0xbe480000,0x3e480000,0xbf7b3f80,0xbf553f6d,0xbf0e3ec4,0x3f0ebec4,0xbf553f6d,
0xbf0e3f35,0xbf553f35,0x3f55bf35,0xbf0e3f35,0xbe483ec4,0xbf7b3f6d,0x3f7bbf6d,0xbe483ec4,0x3f7fbf80,0x3dc90000,0x3f22bf35,0x3f46bf35,
0x3f75bf7b,0x3e95be48,0x3ef1bf0e,0x3f62bf55,0x3f62bf6d,0x3ef1bec4,0x3e95bec4,0x3f75bf6d,0x3f46bf55,0x3f22bf0e,0x3dc9be48,0x3f7fbf7b,
0x3f803f80,0xbf803f80,0x3f803f80,0xbf803f80,0x3f803f80,0xbf803f80,0x3f803f80,0xbf803f80,0x3f803f80,0xbf803f80,0x3f803f80,0xbf803f80,
0x3f803f80,0xbf803f80,0x3f803f80,0xbf803f80,0x3dc90000,0x3f7f3f80,0x3f463f35,0x3f223f35,0x3e953e48,0x3f753f7b,0x3f623f55,0x3ef13f0e,
0x3ef13ec4,0x3f623f6d,0x3f753f6d,0x3e953ec4,0x3f223f0e,0x3f463f55,0x3f7f3f7b,0x3dc93e48,0xbf7bbf80,0x3e480000,0x3e480000,0x3f7b3f80,
0xbf55bf6d,0x3f0e3ec4,0x3f0e3ec4,0x3f553f6d,0xbf0ebf35,0x3f553f35,0x3f553f35,0x3f0e3f35,0xbe48bec4,0x3f7b3f6d,0x3f7b3f6d,0x3e483ec4,
0xbe950000,0xbf75bf80,0xbef1bf35,0x3f623f35,0xbf46bf0e,0xbf22bf55,0x3dc9be48,0x3f7f3f7b,0xbf7fbf6d,0xbdc9bec4,0x3f223ec4,0x3f463f6d,
0xbf62bf7b,0x3ef13e48,0x3f753f55,0x3e953f0e,0x3f6d3f80,0xbec40000,0xbf6dbf80,0x3ec40000,0x3ec43f35,0xbf6dbf35,0xbec4bf35,0x3f6d3f35,
0xbec40000,0xbf6dbf80,0x3ec40000,0x3f6d3f80,0xbf6dbf35,0xbec4bf35,0x3f6d3f35,0x3ec43f35,0x3ef10000,0x3f623f80,0xbf75bf35,0xbe95bf35,
0x3f7f3f55,0x3dc93f0e,0xbf46bf7b,0x3f223e48,0x3f223f6d,0xbf46bec4,0x3dc9bec4,0x3f7f3f6d,0xbe953e48,0xbf75bf7b,0x3f623f0e,0x3ef13f55,
0xbf55bf80,0x3f0e0000,0xbf0e0000,0xbf55bf80,0x3e48bec4,0x3f7b3f6d,0xbf7bbf6d,0x3e48bec4,0x3f7b3f35,0x3e483f35,0xbe48bf35,0x3f7b3f35,
0x3f0e3f6d,0xbf55bec4,0x3f553ec4,0x3f0e3f6d,0xbf220000,0xbf46bf80,0x3dc93f35,0xbf7fbf35,0xbf62bf7b,0x3ef1be48,0xbf75bf0e,0xbe95bf55,
0x3e95bec4,0x3f753f6d,0xbef1bf6d,0x3f623ec4,0x3f7f3f55,0xbdc93f0e,0x3f463e48,0x3f223f7b,0x3f353f80,0xbf350000,0x3f353f80,0xbf350000,
0xbf350000,0xbf35bf80,0xbf350000,0xbf35bf80,0xbf35bf80,0x3f350000,0xbf35bf80,0x3f350000,0x3f350000,0x3f353f80,0x3f350000,0x3f353f80,
0x3f460000,0x3f223f80,0x3f7f3f35,0xbdc93f35,0x3ef13f7b,0xbf62be48,0xbe953f0e,0xbf75bf55,0xbf75bec4,0xbe95bf6d,0xbf62bf6d,0x3ef1bec4,
0xbdc9bf55,0x3f7f3f0e,0x3f22be48,0x3f463f7b,0xbf0ebf80,0x3f550000,0x3f550000,0x3f0e3f80,0x3f7b3ec4,0x3e483f6d,0x3e483f6d,0xbf7bbec4,
0xbe483f35,0xbf7bbf35,0xbf7bbf35,0x3e48bf35,0xbf55bf6d,0x3f0ebec4,0x3f0ebec4,0x3f553f6d,0xbf620000,0xbef1bf80,0x3e95bf35,0x3f753f35,
0x3dc9bf55,0x3f7f3f0e,0x3f223f7b,0xbf463e48,0x3f463f6d,0xbf223ec4,0xbf7fbec4,0xbdc9bf6d,0xbf75be48,0xbe95bf7b,0x3ef1bf0e,0x3f623f55,
0x3ec43f80,0xbf6d0000,0xbec4bf80,0x3f6d0000,0xbf6dbf35,0x3ec4bf35,0x3f6d3f35,0xbec43f35,0x3f6d0000,0x3ec43f80,0xbf6d0000,0xbec4bf80,
0xbec43f35,0xbf6dbf35,0x3ec4bf35,0x3f6d3f35,0x3f750000,0x3e953f80,0xbf62bf35,0x3ef1bf35,0xbf223f0e,0xbf46bf55,0x3f7f3e48,0x3dc93f7b,
0x3dc9bf6d,0x3f7f3ec4,0xbf463ec4,0xbf22bf6d,0x3ef13f7b,0xbf623e48,0x3e95bf55,0x3f753f0e,0xbe48bf80,0x3f7b0000,0xbf7b0000,0xbe48bf80,
0x3f0e3f6d,0xbf553ec4,0x3f55bec4,0x3f0e3f6d,0xbf55bf35,0x3f0ebf35,0xbf0e3f35,0xbf55bf35,0x3f7b3ec4,0xbe483f6d,0x3e48bf6d,0x3f7b3ec4,
0xbf7f0000,0xbdc9bf80,0xbf223f35,0xbf46bf35,0x3f75be48,0x3e953f7b,0x3ef1bf55,0x3f623f0e,0xbf623ec4,0xbef1bf6d,0xbe953f6d,0xbf75bec4,
0x3f46bf0e,0x3f223f55,0x3dc9bf7b,0x3f7f3e48,0x3f80,0xbf800000,0x3f80,0xbf800000,0xbf80,0x3f800000,0xbf80,0x3f800000,
0x3f80,0xbf800000,0x3f80,0xbf800000,0xbf80,0x3f800000,0xbf80,0x3f800000,0x3f7f0000,0xbdc93f80,0x3f223f35,0xbf463f35,
0xbf75be48,0x3e95bf7b,0xbef1bf55,0x3f62bf0e,0x3f623ec4,0xbef13f6d,0x3e953f6d,0xbf753ec4,0xbf46bf0e,0x3f22bf55,0xbdc9bf7b,0x3f7fbe48,
0x3e48bf80,0x3f7b0000,0x3f7b0000,0xbe483f80,0xbf0e3f6d,0xbf55bec4,0xbf55bec4,0x3f0ebf6d,0x3f55bf35,0x3f0e3f35,0x3f0e3f35,0xbf553f35,
0xbf7b3ec4,0xbe48bf6d,0xbe48bf6d,0x3f7bbec4,0xbf750000,0x3e95bf80,0x3f62bf35,0x3ef13f35,0x3f223f0e,0xbf463f55,0xbf7f3e48,0x3dc9bf7b,
0xbdc9bf6d,0x3f7fbec4,0x3f463ec4,0xbf223f6d,0xbef13f7b,0xbf62be48,0xbe95bf55,0x3f75bf0e,0xbec43f80,0xbf6d0000,0x3ec4bf80,0x3f6d0000,
0x3f6dbf35,0x3ec43f35,0xbf6d3f35,0xbec4bf35,0xbf6d0000,0x3ec4bf80,0x3f6d0000,0xbec43f80,0x3ec43f35,0xbf6d3f35,0xbec4bf35,0x3f6dbf35,
0x3f620000,0xbef13f80,0xbe95bf35,0x3f75bf35,0xbdc9bf55,0x3f7fbf0e,0xbf223f7b,0xbf46be48,0xbf463f6d,0xbf22bec4,0x3f7fbec4,0xbdc93f6d,
0x3f75be48,0xbe953f7b,0xbef1bf0e,0x3f62bf55,0x3f0ebf80,0x3f550000,0xbf550000,0x3f0ebf80,0xbf7b3ec4,0x3e48bf6d,0xbe483f6d,0xbf7b3ec4,
0x3e483f35,0xbf7b3f35,0x3f7bbf35,0x3e483f35,0x3f55bf6d,0x3f0e3ec4,0xbf0ebec4,0x3f55bf6d,0xbf460000,0x3f22bf80,0xbf7f3f35,0xbdc9bf35,
0xbef13f7b,0xbf623e48,0x3e953f0e,0xbf753f55,0x3f75bec4,0xbe953f6d,0x3f62bf6d,0x3ef13ec4,0x3dc9bf55,0x3f7fbf0e,0xbf22be48,0x3f46bf7b,
0xbf353f80,0xbf350000,0xbf353f80,0xbf350000,0x3f350000,0xbf353f80,0x3f350000,0xbf353f80,0x3f35bf80,0x3f350000,0x3f35bf80,0x3f350000,
0xbf350000,0x3f35bf80,0xbf350000,0x3f35bf80,0x3f220000,0xbf463f80,0xbdc93f35,0xbf7f3f35,0x3f62bf7b,0x3ef13e48,0x3f75bf0e,0xbe953f55,
0xbe95bec4,0x3f75bf6d,0x3ef1bf6d,0x3f62bec4,0xbf7f3f55,0xbdc9bf0e,0xbf463e48,0x3f22bf7b,0x3f55bf80,0x3f0e0000,0x3f0e0000,0xbf553f80,
0xbe48bec4,0x3f7bbf6d,0x3f7bbf6d,0x3e483ec4,0xbf7b3f35,0x3e48bf35,0x3e48bf35,0x3f7bbf35,0xbf0e3f6d,0xbf553ec4,0xbf553ec4,0x3f0ebf6d,
0xbef10000,0x3f62bf80,0x3f75bf35,0xbe953f35,0xbf7f3f55,0x3dc9bf0e,0x3f46bf7b,0x3f22be48,0xbf223f6d,0xbf463ec4,0xbdc9bec4,0x3f7fbf6d,
0x3e953e48,0xbf753f7b,0xbf623f0e,0x3ef1bf55,0xbf6d3f80,0xbec40000,0x3f6dbf80,0x3ec40000,0xbec43f35,0xbf6d3f35,0x3ec4bf35,0x3f6dbf35,
0x3ec40000,0xbf6d3f80,0xbec40000,0x3f6dbf80,0x3f6dbf35,0xbec43f35,0xbf6d3f35,0x3ec4bf35,0x3e950000,0xbf753f80,0x3ef1bf35,0x3f62bf35,
0x3f46bf0e,0xbf223f55,0xbdc9be48,0x3f7fbf7b,0x3f7fbf6d,0xbdc93ec4,0xbf223ec4,0x3f46bf6d,0x3f62bf7b,0x3ef1be48,0xbf753f55,0x3e95bf0e,
0x3f7bbf80,0x3e480000,0xbe480000,0x3f7bbf80,0x3f55bf6d,0x3f0ebec4,0xbf0e3ec4,0x3f55bf6d,0x3f0ebf35,0x3f55bf35,0xbf553f35,0x3f0ebf35,
0x3e48bec4,0x3f7bbf6d,0xbf7b3f6d,0x3e48bec4,0xbdc90000,0x3f7fbf80,0xbf463f35,0x3f22bf35,0xbe953e48,0x3f75bf7b,0xbf623f55,0x3ef1bf0e,
0xbef13ec4,0x3f62bf6d,0xbf753f6d,0x3e95bec4,0xbf223f0e,0x3f46bf55,0xbf7f3f7b,0x3dc9be48,0x40003f80,0x3fb53f80,0x3f80,0xbfb53f80,
0x40004000,0xbfb50000,0x0,0xbfb5c000,0x40004000,0xbfb5c000,0x0,0x3fb50000,0x40004000,0x3fb50000,0x0,0x3fb54000,
0x3fff3f80,0x3fa23f80,0xbe49bf80,0xbfc6bf80,0x3ff53ffb,0xbfe2bec8,0xbf15bec8,0xbf71bffb,0x3fe23fed,0xbf15bfed,0xbf71bf44,0x3ff53f44,
0x3fc63fd5,0x3fff3f8e,0xbfa2bf8e,0x3e493fd5,0x3ffb3f80,0x3f8e3f80,0xbec83f80,0xbfd53f80,0x3fd53fed,0xbffbbf44,0xbf8ebf44,0xbec8bfed,
0x3f8e3fb5,0x3ec8bfb5,0xbfd5bfb5,0x3ffb3fb5,0x3ec83f44,0x3fd53fed,0xbffbbfed,0xbf8e3f44,0x3ff53f80,0x3f713f80,0xbf15bf80,0xbfe2bf80,
0x3fa23fd5,0xbfffbf8e,0xbfc6bf8e,0x3e49bfd5,0x3e493f44,0x3fa2bf44,0xbfffbfed,0x3fc63fed,0xbf71bec8,0x3f153ffb,0xbfe2bffb,0xbff5bec8,
0x3fed3f80,0x3f443f80,0xbf443f80,0xbfed3f80,0x3f443fb5,0xbfedbfb5,0xbfedbfb5,0x3f44bfb5,0xbf440000,0x3fed0000,0xbfedc000,0x3f444000,
0xbfedbfb5,0xbf443fb5,0xbf44bfb5,0xbfedbfb5,0x3fe23f80,0x3f153f80,0xbf71bf80,0xbff5bf80,0x3e493f8e,0xbfc6bfd5,0xbfffbfd5,0x3fa2bf8e,
0xbfc6bf44,0x3fff3f44,0xbfa2bfed,0xbe493fed,0xbff5bffb,0xbfe23ec8,0x3f15bec8,0xbf71bffb,0x3fd53f80,0x3ec83f80,0xbf8e3f80,0xbffb3f80,
0xbec83f44,0xbf8ebfed,0xbffbbfed,0x3fd5bf44,0xbffbbfb5,0x3fd53fb5,0xbec8bfb5,0xbf8e3fb5,0xbf8ebfed,0xbffbbf44,0x3fd53f44,0x3ec8bfed,
0x3fc63f80,0x3e493f80,0xbfa2bf80,0xbfffbf80,0xbf713ec8,0xbf15bffb,0xbfe2bffb,0x3ff5bec8,0xbff5bfed,0x3f713fed,0x3f15bf44,0xbfe23f44,
0x3e49bf8e,0xbfa2bfd5,0x3fff3fd5,0x3fc6bf8e,0x3f80,0xbfb53f80,0xc0003f80,0xbfb53f80,0xc000,0x3fb50000,0x40000000,0xbfb54000,
0x4000,0x3fb5c000,0xc0000000,0x3fb50000,0xc000,0xbfb50000,0x40000000,0x3fb5c000,0xbe493f80,0xbfc63f80,0xbfffbf80,0xbfa2bf80,
0x3f15bffb,0x3f713ec8,0x3ff53ec8,0xbfe23ffb,0xbf713fed,0x3ff5bfed,0xbfe2bf44,0x3f153f44,0x3fa2bfd5,0xbe49bf8e,0x3fc63f8e,0x3fffbfd5,
0xbec83f80,0xbfd53f80,0xbffb3f80,0xbf8e3f80,0x3f8ebfed,0x3ec83f44,0x3fd53f44,0xbffb3fed,0xbfd53fb5,0x3ffbbfb5,0xbf8ebfb5,0xbec83fb5,
0x3ffbbf44,0x3f8ebfed,0x3ec83fed,0x3fd5bf44,0xbf153f80,0xbfe23f80,0xbff5bf80,0xbf71bf80,0x3fc6bfd5,0xbe493f8e,0x3fa23f8e,0xbfff3fd5,
0xbfff3f44,0x3fc6bf44,0xbe49bfed,0xbfa23fed,0x3fe23ec8,0x3ff5bffb,0xbf713ffb,0x3f153ec8,0xbf443f80,0xbfed3f80,0xbfed3f80,0xbf443f80,
0x3fedbfb5,0xbf443fb5,0x3f443fb5,0xbfed3fb5,0xbfed0000,0x3f440000,0x3f44c000,0xbfed4000,0x3f443fb5,0x3fedbfb5,0xbfed3fb5,0xbf443fb5,
0xbf713f80,0xbff53f80,0xbfe2bf80,0xbf15bf80,0x3fffbf8e,0xbfa23fd5,0x3e493fd5,0xbfc63f8e,0xbfa2bf44,0xbe493f44,0x3fc6bfed,0xbfff3fed,
0xbf153ffb,0x3f71bec8,0xbff53ec8,0xbfe23ffb,0xbf8e3f80,0xbffb3f80,0xbfd53f80,0xbec83f80,0x3ffbbf44,0xbfd53fed,0xbec83fed,0xbf8e3f44,
0xbec8bfb5,0xbf8e3fb5,0x3ffbbfb5,0xbfd53fb5,0xbfd53fed,0xbec83f44,0xbf8ebf44,0xbffb3fed,0xbfa23f80,0xbfff3f80,0xbfc6bf80,0xbe49bf80,
0x3fe2bec8,0xbff53ffb,0xbf713ffb,0xbf153ec8,0x3f15bfed,0xbfe23fed,0x3ff5bf44,0xbf713f44,0xbfff3f8e,0xbfc63fd5,0x3e49bfd5,0xbfa23f8e,
0xc0003f80,0xbfb53f80,0x3f80,0x3fb53f80,0xc0004000,0x3fb50000,0x0,0x3fb5c000,0xc0004000,0x3fb5c000,0x0,0xbfb50000,
0xc0004000,0xbfb50000,0x0,0xbfb54000,0xbfff3f80,0xbfa23f80,0x3e49bf80,0x3fc6bf80,0xbff53ffb,0x3fe2bec8,0x3f15bec8,0x3f71bffb,
0xbfe23fed,0x3f15bfed,0x3f71bf44,0xbff53f44,0xbfc63fd5,0xbfff3f8e,0x3fa2bf8e,0xbe493fd5,0xbffb3f80,0xbf8e3f80,0x3ec83f80,0x3fd53f80,
0xbfd53fed,0x3ffbbf44,0x3f8ebf44,0x3ec8bfed,0xbf8e3fb5,0xbec8bfb5,0x3fd5bfb5,0xbffb3fb5,0xbec83f44,0xbfd53fed,0x3ffbbfed,0x3f8e3f44,
0xbff53f80,0xbf713f80,0x3f15bf80,0x3fe2bf80,0xbfa23fd5,0x3fffbf8e,0x3fc6bf8e,0xbe49bfd5,0xbe493f44,0xbfa2bf44,0x3fffbfed,0xbfc63fed,
0x3f71bec8,0xbf153ffb,0x3fe2bffb,0x3ff5bec8,0xbfed3f80,0xbf443f80,0x3f443f80,0x3fed3f80,0xbf443fb5,0x3fedbfb5,0x3fedbfb5,0xbf44bfb5,
0x3f440000,0xbfed0000,0x3fedc000,0xbf444000,0x3fedbfb5,0x3f443fb5,0x3f44bfb5,0x3fedbfb5,0xbfe23f80,0xbf153f80,0x3f71bf80,0x3ff5bf80,
0xbe493f8e,0x3fc6bfd5,0x3fffbfd5,0xbfa2bf8e,0x3fc6bf44,0xbfff3f44,0x3fa2bfed,0x3e493fed,0x3ff5bffb,0x3fe23ec8,0xbf15bec8,0x3f71bffb,
0xbfd53f80,0xbec83f80,0x3f8e3f80,0x3ffb3f80,0x3ec83f44,0x3f8ebfed,0x3ffbbfed,0xbfd5bf44,0x3ffbbfb5,0xbfd53fb5,0x3ec8bfb5,0x3f8e3fb5,
0x3f8ebfed,0x3ffbbf44,0xbfd53f44,0xbec8bfed,0xbfc63f80,0xbe493f80,0x3fa2bf80,0x3fffbf80,0x3f713ec8,0x3f15bffb,0x3fe2bffb,0xbff5bec8,
0x3ff5bfed,0xbf713fed,0xbf15bf44,0x3fe23f44,0xbe49bf8e,0x3fa2bfd5,0xbfff3fd5,0xbfc6bf8e,0x3f80,0x3fb53f80,0x40003f80,0x3fb53f80,
0xc000,0xbfb50000,0xc0000000,0x3fb54000,0x4000,0xbfb5c000,0x40000000,0xbfb50000,0xc000,0x3fb50000,0xc0000000,0xbfb5c000,
0x3e493f80,0x3fc63f80,0x3fffbf80,0x3fa2bf80,0xbf15bffb,0xbf713ec8,0xbff53ec8,0x3fe23ffb,0x3f713fed,0xbff5bfed,0x3fe2bf44,0xbf153f44,
0xbfa2bfd5,0x3e49bf8e,0xbfc63f8e,0xbfffbfd5,0x3ec83f80,0x3fd53f80,0x3ffb3f80,0x3f8e3f80,0xbf8ebfed,0xbec83f44,0xbfd53f44,0x3ffb3fed,
0x3fd53fb5,0xbffbbfb5,0x3f8ebfb5,0x3ec83fb5,0xbffbbf44,0xbf8ebfed,0xbec83fed,0xbfd5bf44,0x3f153f80,0x3fe23f80,0x3ff5bf80,0x3f71bf80,
0xbfc6bfd5,0x3e493f8e,0xbfa23f8e,0x3fff3fd5,0x3fff3f44,0xbfc6bf44,0x3e49bfed,0x3fa23fed,0xbfe23ec8,0xbff5bffb,0x3f713ffb,0xbf153ec8,
0x3f443f80,0x3fed3f80,0x3fed3f80,0x3f443f80,0xbfedbfb5,0x3f443fb5,0xbf443fb5,0x3fed3fb5,0x3fed0000,0xbf440000,0xbf44c000,0x3fed4000,
0xbf443fb5,0xbfedbfb5,0x3fed3fb5,0x3f443fb5,0x3f713f80,0x3ff53f80,0x3fe2bf80,0x3f15bf80,0xbfffbf8e,0x3fa23fd5,0xbe493fd5,0x3fc63f8e,
0x3fa2bf44,0x3e493f44,0xbfc6bfed,0x3fff3fed,0x3f153ffb,0xbf71bec8,0x3ff53ec8,0x3fe23ffb,0x3f8e3f80,0x3ffb3f80,0x3fd53f80,0x3ec83f80,
0xbffbbf44,0x3fd53fed,0x3ec83fed,0x3f8e3f44,0x3ec8bfb5,0x3f8e3fb5,0xbffbbfb5,0x3fd53fb5,0x3fd53fed,0x3ec83f44,0x3f8ebf44,0x3ffb3fed,
0x3fa23f80,0x3fff3f80,0x3fc6bf80,0x3e49bf80,0xbfe2bec8,0x3ff53ffb,0x3f713ffb,0x3f153ec8,0xbf15bfed,0x3fe23fed,0xbff5bf44,0x3f713f44,
0x3fff3f8e,0x3fc63fd5,0xbe49bfd5,0x3fa23f8e,0x40004000,0x3fb54000,0x0,0xbfb50000,0x40004000,0xbfb50000,0x0,0xbfb5c000,
0x40004000,0xbfb5c000,0x0,0x3fb50000,0x40004000,0x3fb50000,0x0,0x3fb54000,0x3fa23fb5,0xbe493fb5,0xbfc6bfb5,0xbfffbfb5,
0x3f713f8e,0xbff5bfd5,0xbfe2bfd5,0x3f15bf8e,0x3f153f44,0x3f71bf44,0xbff5bfed,0x3fe23fed,0x3e493ec8,0x3fc63ffb,0xbfffbffb,0xbfa23ec8,
0xbec80000,0xbfd50000,0xbffbc000,0xbf8ec000,0xbf8ebf44,0xbec8bfed,0xbfd5bfed,0x3ffb3f44,0xbfd5bfb5,0x3ffb3fb5,0xbf8ebfb5,0xbec83fb5,
0xbffbbfed,0xbf8e3f44,0xbec8bf44,0xbfd5bfed,0xbfe2bfb5,0xbff5bfb5,0xbf71bfb5,0x3f15bfb5,0xbfffbffb,0x3fc6bec8,0x3e49bec8,0x3fa23ffb,
0xbfc6bfed,0x3e493fed,0x3fa23f44,0xbfffbf44,0xbf15bf8e,0xbfe2bfd5,0x3ff53fd5,0x3f71bf8e,0xbfedc000,0xbf44c000,0x3f440000,0x3fed0000,
0xbf44bfb5,0x3fed3fb5,0x3fed3fb5,0xbf443fb5,0x3f440000,0xbfed0000,0x3fed4000,0xbf44c000,0x3fed3fb5,0x3f44bfb5,0x3f443fb5,0x3fed3fb5,
0xbf15bfb5,0x3f71bfb5,0x3ff53fb5,0x3fe23fb5,0x3fa23ec8,0x3e493ffb,0x3fc63ffb,0xbfffbec8,0x3fff3fed,0xbfa2bfed,0xbe493f44,0x3fc6bf44,
0x3f713fd5,0x3ff53f8e,0xbfe2bf8e,0xbf153fd5,0x3f8e0000,0x3ffb0000,0x3fd54000,0x3ec84000,0x3ffb3fed,0xbfd53f44,0xbec83f44,0xbf8ebfed,
0x3ec83fb5,0x3f8ebfb5,0xbffbbfb5,0x3fd53fb5,0xbfd5bf44,0xbec83fed,0xbf8ebfed,0xbffbbf44,0x3fff3fb5,0x3fc63fb5,0x3e493fb5,0xbfa23fb5,
0x3f153fd5,0xbfe2bf8e,0xbff5bf8e,0x3f71bfd5,0xbfe2bf44,0x3ff53f44,0xbf71bfed,0xbf153fed,0xbfa2bffb,0xbfffbec8,0x3fc63ec8,0x3e49bffb,
0x4000,0xbfb54000,0xc0000000,0xbfb50000,0xc000,0x3fb50000,0x40000000,0xbfb54000,0x4000,0x3fb5c000,0xc0000000,0x3fb50000,
0xc000,0xbfb50000,0x40000000,0x3fb5c000,0xbfc63fb5,0xbfff3fb5,0xbfa2bfb5,0x3e49bfb5,0x3fe2bf8e,0xbf153fd5,0x3f713fd5,0xbff53f8e,
0xbff53f44,0x3fe2bf44,0xbf15bfed,0xbf713fed,0x3fffbec8,0x3fa2bffb,0x3e493ffb,0x3fc6bec8,0xbffb0000,0xbf8e0000,0x3ec8c000,0x3fd5c000,
0x3fd53f44,0xbffb3fed,0xbf8e3fed,0xbec8bf44,0xbf8ebfb5,0xbec83fb5,0x3fd5bfb5,0xbffb3fb5,0x3ec83fed,0x3fd5bf44,0xbffb3f44,0xbf8e3fed,
0xbf71bfb5,0x3f15bfb5,0x3fe2bfb5,0x3ff5bfb5,0xbe493ffb,0xbfa23ec8,0xbfff3ec8,0x3fc6bffb,0x3fa2bfed,0xbfff3fed,0x3fc63f44,0xbe49bf44,
0xbff53f8e,0xbf713fd5,0xbf15bfd5,0xbfe23f8e,0x3f44c000,0x3fedc000,0x3fed0000,0x3f440000,0xbfed3fb5,0x3f44bfb5,0xbf44bfb5,0x3fedbfb5,
0x3fed0000,0xbf440000,0xbf444000,0x3fedc000,0xbf44bfb5,0xbfed3fb5,0x3fedbfb5,0x3f44bfb5,0x3ff5bfb5,0x3fe2bfb5,0x3f153fb5,0xbf713fb5,
0xbfc6bec8,0x3fffbffb,0x3fa2bffb,0x3e493ec8,0xbe493fed,0x3fc6bfed,0xbfff3f44,0x3fa2bf44,0x3fe2bfd5,0x3f15bf8e,0x3f713f8e,0x3ff5bfd5,
0x3fd50000,0x3ec80000,0xbf8e4000,0xbffb4000,0x3ec8bfed,0x3f8ebf44,0x3ffbbf44,0xbfd53fed,0xbffb3fb5,0x3fd5bfb5,0xbec8bfb5,0xbf8e3fb5,
0x3f8e3f44,0x3ffbbfed,0xbfd53fed,0xbec83f44,0x3e493fb5,0xbfa23fb5,0xbfff3fb5,0xbfc63fb5,0x3ff5bfd5,0xbf713f8e,0x3f153f8e,0xbfe23fd5,
0xbf71bf44,0xbf153f44,0x3fe2bfed,0xbff53fed,0xbfc63ffb,0xbe493ec8,0xbfa2bec8,0xbfff3ffb,0xc0004000,0xbfb54000,0x0,0x3fb50000,
0xc0004000,0x3fb50000,0x0,0x3fb5c000,0xc0004000,0x3fb5c000,0x0,0xbfb50000,0xc0004000,0xbfb50000,0x0,0xbfb54000,
0xbfa23fb5,0x3e493fb5,0x3fc6bfb5,0x3fffbfb5,0xbf713f8e,0x3ff5bfd5,0x3fe2bfd5,0xbf15bf8e,0xbf153f44,0xbf71bf44,0x3ff5bfed,0xbfe23fed,
0xbe493ec8,0xbfc63ffb,0x3fffbffb,0x3fa23ec8,0x3ec80000,0x3fd50000,0x3ffbc000,0x3f8ec000,0x3f8ebf44,0x3ec8bfed,0x3fd5bfed,0xbffb3f44,
0x3fd5bfb5,0xbffb3fb5,0x3f8ebfb5,0x3ec83fb5,0x3ffbbfed,0x3f8e3f44,0x3ec8bf44,0x3fd5bfed,0x3fe2bfb5,0x3ff5bfb5,0x3f71bfb5,0xbf15bfb5,
0x3fffbffb,0xbfc6bec8,0xbe49bec8,0xbfa23ffb,0x3fc6bfed,0xbe493fed,0xbfa23f44,0x3fffbf44,0x3f15bf8e,0x3fe2bfd5,0xbff53fd5,0xbf71bf8e,
0x3fedc000,0x3f44c000,0xbf440000,0xbfed0000,0x3f44bfb5,0xbfed3fb5,0xbfed3fb5,0x3f443fb5,0xbf440000,0x3fed0000,0xbfed4000,0x3f44c000,
0xbfed3fb5,0xbf44bfb5,0xbf443fb5,0xbfed3fb5,0x3f15bfb5,0xbf71bfb5,0xbff53fb5,0xbfe23fb5,0xbfa23ec8,0xbe493ffb,0xbfc63ffb,0x3fffbec8,
0xbfff3fed,0x3fa2bfed,0x3e493f44,0xbfc6bf44,0xbf713fd5,0xbff53f8e,0x3fe2bf8e,0x3f153fd5,0xbf8e0000,0xbffb0000,0xbfd54000,0xbec84000,
0xbffb3fed,0x3fd53f44,0x3ec83f44,0x3f8ebfed,0xbec83fb5,0xbf8ebfb5,0x3ffbbfb5,0xbfd53fb5,0x3fd5bf44,0x3ec83fed,0x3f8ebfed,0x3ffbbf44,
0xbfff3fb5,0xbfc63fb5,0xbe493fb5,0x3fa23fb5,0xbf153fd5,0x3fe2bf8e,0x3ff5bf8e,0xbf71bfd5,0x3fe2bf44,0xbff53f44,0x3f71bfed,0x3f153fed,
0x3fa2bffb,0x3fffbec8,0xbfc63ec8,0xbe49bffb,0x4000,0x3fb54000,0x40000000,0x3fb50000,0xc000,0xbfb50000,0xc0000000,0x3fb54000,
0x4000,0xbfb5c000,0x40000000,0xbfb50000,0xc000,0x3fb50000,0xc0000000,0xbfb5c000,0x3fc63fb5,0x3fff3fb5,0x3fa2bfb5,0xbe49bfb5,
0xbfe2bf8e,0x3f153fd5,0xbf713fd5,0x3ff53f8e,0x3ff53f44,0xbfe2bf44,0x3f15bfed,0x3f713fed,0xbfffbec8,0xbfa2bffb,0xbe493ffb,0xbfc6bec8,
0x3ffb0000,0x3f8e0000,0xbec8c000,0xbfd5c000,0xbfd53f44,0x3ffb3fed,0x3f8e3fed,0x3ec8bf44,0x3f8ebfb5,0x3ec83fb5,0xbfd5bfb5,0x3ffb3fb5,
0xbec83fed,0xbfd5bf44,0x3ffb3f44,0x3f8e3fed,0x3f71bfb5,0xbf15bfb5,0xbfe2bfb5,0xbff5bfb5,0x3e493ffb,0x3fa23ec8,0x3fff3ec8,0xbfc6bffb,
0xbfa2bfed,0x3fff3fed,0xbfc63f44,0x3e49bf44,0x3ff53f8e,0x3f713fd5,0x3f15bfd5,0x3fe23f8e,0xbf44c000,0xbfedc000,0xbfed0000,0xbf440000,
0x3fed3fb5,0xbf44bfb5,0x3f44bfb5,0xbfedbfb5,0xbfed0000,0x3f440000,0x3f444000,0xbfedc000,0x3f44bfb5,0x3fed3fb5,0xbfedbfb5,0xbf44bfb5,
0xbff5bfb5,0xbfe2bfb5,0xbf153fb5,0x3f713fb5,0x3fc6bec8,0xbfffbffb,0xbfa2bffb,0xbe493ec8,0x3e493fed,0xbfc6bfed,0x3fff3f44,0xbfa2bf44,
0xbfe2bfd5,0xbf15bf8e,0xbf713f8e,0xbff5bfd5,0xbfd50000,0xbec80000,0x3f8e4000,0x3ffb4000,0xbec8bfed,0xbf8ebf44,0xbffbbf44,0x3fd53fed,
0x3ffb3fb5,0xbfd5bfb5,0x3ec8bfb5,0x3f8e3fb5,0xbf8e3f44,0xbffbbfed,0x3fd53fed,0x3ec83f44,0xbe493fb5,0x3fa23fb5,0x3fff3fb5,0x3fc63fb5,
0xbff5bfd5,0x3f713f8e,0xbf153f8e,0x3fe23fd5,0x3f71bf44,0x3f153f44,0xbfe2bfed,0x3ff53fed,0x3fc63ffb,0x3e493ec8,0x3fa2bec8,0x3fff3ffb,
0x40004000,0x3fb54000,0x0,0xbfb50000,0x40004000,0xbfb50000,0x0,0xbfb5c000,0x40004000,0xbfb5c000,0x0,0x3fb50000,
0x40004000,0x3fb50000,0x0,0x3fb54000,0xbe490000,0xbfc60000,0xbfffc000,0xbfa2c000,0xbf15bec8,0xbf71bffb,0xbff5bffb,0x3fe23ec8,
0xbf71bf44,0x3ff53f44,0xbfe2bfed,0x3f153fed,0xbfa2bf8e,0x3e493fd5,0xbfc6bfd5,0xbfffbf8e,0xbffbc000,0xbf8ec000,0x3ec80000,0x3fd50000,
0xbfd5bfed,0x3ffb3f44,0x3f8e3f44,0x3ec83fed,0xbf8ebfb5,0xbec83fb5,0x3fd53fb5,0xbffbbfb5,0xbec8bf44,0xbfd5bfed,0x3ffb3fed,0x3f8ebf44,
0x3f150000,0x3fe20000,0x3ff54000,0x3f714000,0x3fc63f8e,0xbe493fd5,0x3fa23fd5,0xbfffbf8e,0x3fff3fed,0xbfc6bfed,0x3e493f44,0x3fa2bf44,
0x3fe23ffb,0x3ff53ec8,0xbf71bec8,0x3f153ffb,0x3fed4000,0x3f444000,0xbf440000,0xbfed0000,0x3f443fb5,0xbfedbfb5,0xbfedbfb5,0x3f44bfb5,
0xbf440000,0x3fed0000,0xbfedc000,0x3f444000,0xbfedbfb5,0xbf443fb5,0xbf44bfb5,0xbfedbfb5,0xbf710000,0xbff50000,0xbfe2c000,0xbf15c000,
0xbfffbfd5,0x3fa2bf8e,0xbe49bf8e,0x3fc63fd5,0xbfa2bfed,0xbe493fed,0x3fc63f44,0xbfffbf44,0x3f15bec8,0xbf71bffb,0x3ff53ffb,0x3fe2bec8,
0xbfd5c000,0xbec8c000,0x3f8e0000,0x3ffb0000,0x3ec8bf44,0x3f8e3fed,0x3ffb3fed,0xbfd53f44,0x3ffb3fb5,0xbfd5bfb5,0x3ec83fb5,0x3f8ebfb5,
0x3f8e3fed,0x3ffb3f44,0xbfd5bf44,0xbec83fed,0x3fa20000,0x3fff0000,0x3fc64000,0x3e494000,0x3fe23ffb,0xbff53ec8,0xbf713ec8,0xbf15bffb,
0xbf153f44,0x3fe2bf44,0xbff5bfed,0x3f713fed,0xbfffbfd5,0xbfc63f8e,0x3e49bf8e,0xbfa2bfd5,0x4000,0xbfb54000,0xc0000000,0xbfb50000,
0xc000,0x3fb50000,0x40000000,0xbfb54000,0x4000,0x3fb5c000,0xc0000000,0x3fb50000,0xc000,0xbfb50000,0x40000000,0x3fb5c000,
0xbfff0000,0xbfa20000,0x3e49c000,0x3fc6c000,0x3ff53ec8,0xbfe23ffb,0xbf153ffb,0xbf71bec8,0xbfe2bf44,0x3f153f44,0x3f71bfed,0xbff53fed,
0x3fc63f8e,0x3fffbfd5,0xbfa23fd5,0x3e493f8e,0x3ec8c000,0x3fd5c000,0x3ffb0000,0x3f8e0000,0xbf8e3fed,0xbec8bf44,0xbfd5bf44,0x3ffbbfed,
0x3fd5bfb5,0xbffb3fb5,0x3f8e3fb5,0x3ec8bfb5,0xbffb3f44,0xbf8e3fed,0xbec8bfed,0xbfd53f44,0x3ff50000,0x3f710000,0xbf154000,0xbfe24000,
0xbfa2bf8e,0x3fffbfd5,0x3fc6bfd5,0xbe493f8e,0x3e493fed,0x3fa2bfed,0xbfff3f44,0x3fc6bf44,0x3f71bffb,0xbf15bec8,0x3fe23ec8,0x3ff5bffb,
0xbf444000,0xbfed4000,0xbfed0000,0xbf440000,0x3fedbfb5,0xbf443fb5,0x3f443fb5,0xbfed3fb5,0xbfed0000,0x3f440000,0x3f44c000,0xbfed4000,
0x3f443fb5,0x3fedbfb5,0xbfed3fb5,0xbf443fb5,0xbfe20000,0xbf150000,0x3f71c000,0x3ff5c000,0x3e493fd5,0xbfc63f8e,0xbfff3f8e,0x3fa2bfd5,
0x3fc6bfed,0xbfff3fed,0x3fa23f44,0x3e49bf44,0xbff53ec8,0xbfe23ffb,0x3f15bffb,0xbf713ec8,0x3f8ec000,0x3ffbc000,0x3fd50000,0x3ec80000,
0xbffb3f44,0x3fd5bfed,0x3ec8bfed,0x3f8ebf44,0x3ec83fb5,0x3f8ebfb5,0xbffb3fb5,0x3fd5bfb5,0x3fd5bfed,0x3ec8bf44,0x3f8e3f44,0x3ffbbfed,
0x3fc60000,0x3e490000,0xbfa24000,0xbfff4000,0x3f71bffb,0x3f15bec8,0x3fe2bec8,0xbff53ffb,0xbff53f44,0x3f71bf44,0x3f15bfed,0xbfe23fed,
0xbe493fd5,0x3fa2bf8e,0xbfff3f8e,0xbfc63fd5,0xc0004000,0xbfb54000,0x0,0x3fb50000,0xc0004000,0x3fb50000,0x0,0x3fb5c000,
0xc0004000,0x3fb5c000,0x0,0xbfb50000,0xc0004000,0xbfb50000,0x0,0xbfb54000,0x3e490000,0x3fc60000,0x3fffc000,0x3fa2c000,
0x3f15bec8,0x3f71bffb,0x3ff5bffb,0xbfe23ec8,0x3f71bf44,0xbff53f44,0x3fe2bfed,0xbf153fed,0x3fa2bf8e,0xbe493fd5,0x3fc6bfd5,0x3fffbf8e,
0x3ffbc000,0x3f8ec000,0xbec80000,0xbfd50000,0x3fd5bfed,0xbffb3f44,0xbf8e3f44,0xbec83fed,0x3f8ebfb5,0x3ec83fb5,0xbfd53fb5,0x3ffbbfb5,
0x3ec8bf44,0x3fd5bfed,0xbffb3fed,0xbf8ebf44,0xbf150000,0xbfe20000,0xbff54000,0xbf714000,0xbfc63f8e,0x3e493fd5,0xbfa23fd5,0x3fffbf8e,
0xbfff3fed,0x3fc6bfed,0xbe493f44,0xbfa2bf44,0xbfe23ffb,0xbff53ec8,0x3f71bec8,0xbf153ffb,0xbfed4000,0xbf444000,0x3f440000,0x3fed0000,
0xbf443fb5,0x3fedbfb5,0x3fedbfb5,0xbf44bfb5,0x3f440000,0xbfed0000,0x3fedc000,0xbf444000,0x3fedbfb5,0x3f443fb5,0x3f44bfb5,0x3fedbfb5,
0x3f710000,0x3ff50000,0x3fe2c000,0x3f15c000,0x3fffbfd5,0xbfa2bf8e,0x3e49bf8e,0xbfc63fd5,0x3fa2bfed,0x3e493fed,0xbfc63f44,0x3fffbf44,
0xbf15bec8,0x3f71bffb,0xbff53ffb,0xbfe2bec8,0x3fd5c000,0x3ec8c000,0xbf8e0000,0xbffb0000,0xbec8bf44,0xbf8e3fed,0xbffb3fed,0x3fd53f44,
0xbffb3fb5,0x3fd5bfb5,0xbec83fb5,0xbf8ebfb5,0xbf8e3fed,0xbffb3f44,0x3fd5bf44,0x3ec83fed,0xbfa20000,0xbfff0000,0xbfc64000,0xbe494000,
0xbfe23ffb,0x3ff53ec8,0x3f713ec8,0x3f15bffb,0x3f153f44,0xbfe2bf44,0x3ff5bfed,0xbf713fed,0x3fffbfd5,0x3fc63f8e,0xbe49bf8e,0x3fa2bfd5,
0x4000,0x3fb54000,0x40000000,0x3fb50000,0xc000,0xbfb50000,0xc0000000,0x3fb54000,0x4000,0xbfb5c000,0x40000000,0xbfb50000,
0xc000,0x3fb50000,0xc0000000,0xbfb5c000,0x3fff0000,0x3fa20000,0xbe49c000,0xbfc6c000,0xbff53ec8,0x3fe23ffb,0x3f153ffb,0x3f71bec8,
0x3fe2bf44,0xbf153f44,0xbf71bfed,0x3ff53fed,0xbfc63f8e,0xbfffbfd5,0x3fa23fd5,0xbe493f8e,0xbec8c000,0xbfd5c000,0xbffb0000,0xbf8e0000,
0x3f8e3fed,0x3ec8bf44,0x3fd5bf44,0xbffbbfed,0xbfd5bfb5,0x3ffb3fb5,0xbf8e3fb5,0xbec8bfb5,0x3ffb3f44,0x3f8e3fed,0x3ec8bfed,0x3fd53f44,
0xbff50000,0xbf710000,0x3f154000,0x3fe24000,0x3fa2bf8e,0xbfffbfd5,0xbfc6bfd5,0x3e493f8e,0xbe493fed,0xbfa2bfed,0x3fff3f44,0xbfc6bf44,
0xbf71bffb,0x3f15bec8,0xbfe23ec8,0xbff5bffb,0x3f444000,0x3fed4000,0x3fed0000,0x3f440000,0xbfedbfb5,0x3f443fb5,0xbf443fb5,0x3fed3fb5,
0x3fed0000,0xbf440000,0xbf44c000,0x3fed4000,0xbf443fb5,0xbfedbfb5,0x3fed3fb5,0x3f443fb5,0x3fe20000,0x3f150000,0xbf71c000,0xbff5c000,
0xbe493fd5,0x3fc63f8e,0x3fff3f8e,0xbfa2bfd5,0xbfc6bfed,0x3fff3fed,0xbfa23f44,0xbe49bf44,0x3ff53ec8,0x3fe23ffb,0xbf15bffb,0x3f713ec8,
0xbf8ec000,0xbffbc000,0xbfd50000,0xbec80000,0x3ffb3f44,0xbfd5bfed,0xbec8bfed,0xbf8ebf44,0xbec83fb5,0xbf8ebfb5,0x3ffb3fb5,0xbfd5bfb5,
0xbfd5bfed,0xbec8bf44,0xbf8e3f44,0xbffbbfed,0xbfc60000,0xbe490000,0x3fa24000,0x3fff4000,0xbf71bffb,0xbf15bec8,0xbfe2bec8,0x3ff53ffb,
0x3ff53f44,0xbf71bf44,0xbf15bfed,0x3fe23fed,0x3e493fd5,0xbfa2bf8e,0x3fff3f8e,0x3fc63fd5,0x40004000,0x3fb54000,0x0,0xbfb50000,
0x40004000,0xbfb50000,0x0,0xbfb5c000,0x40004000,0xbfb5c000,0x0,0x3fb50000,0x40004000,0x3fb50000,0x0,0x3fb54000,
0xbfc6bfb5,0xbfffbfb5,0xbfa2bfb5,0x3e49bfb5,0xbfe2bfd5,0x3f15bf8e,0xbf71bf8e,0x3ff53fd5,0xbff5bfed,0x3fe23fed,0xbf15bf44,0xbf713f44,
0xbfffbffb,0xbfa23ec8,0xbe49bec8,0xbfc6bffb,0x3ec80000,0x3fd50000,0x3ffb4000,0x3f8e4000,0x3f8e3f44,0x3ec83fed,0x3fd53fed,0xbffbbf44,
0x3fd53fb5,0xbffbbfb5,0x3f8e3fb5,0x3ec8bfb5,0x3ffb3fed,0x3f8ebf44,0x3ec83f44,0x3fd53fed,0x3f713fb5,0xbf153fb5,0xbfe2bfb5,0xbff5bfb5,
0xbe493ec8,0xbfa2bffb,0xbfffbffb,0x3fc6bec8,0xbfa2bf44,0x3fff3f44,0xbfc6bfed,0x3e493fed,0xbff5bfd5,0xbf713f8e,0xbf15bf8e,0xbfe2bfd5,
0xbfedc000,0xbf44c000,0x3f440000,0x3fed0000,0xbf44bfb5,0x3fed3fb5,0x3fed3fb5,0xbf443fb5,0x3f440000,0xbfed0000,0x3fed4000,0xbf44c000,
0x3fed3fb5,0x3f44bfb5,0x3f443fb5,0x3fed3fb5,0x3ff53fb5,0x3fe23fb5,0x3f153fb5,0xbf713fb5,0x3fc63ffb,0xbfffbec8,0xbfa2bec8,0xbe49bffb,
0xbe493f44,0x3fc6bf44,0xbfffbfed,0x3fa23fed,0xbfe2bf8e,0xbf153fd5,0xbf71bfd5,0xbff5bf8e,0xbf8e0000,0xbffb0000,0xbfd5c000,0xbec8c000,
0xbffbbfed,0x3fd5bf44,0x3ec8bf44,0x3f8e3fed,0xbec8bfb5,0xbf8e3fb5,0x3ffb3fb5,0xbfd5bfb5,0x3fd53f44,0x3ec8bfed,0x3f8e3fed,0x3ffb3f44,
0xbe49bfb5,0x3fa2bfb5,0x3fff3fb5,0x3fc63fb5,0x3ff53f8e,0xbf713fd5,0x3f153fd5,0xbfe2bf8e,0x3f713fed,0x3f15bfed,0xbfe2bf44,0x3ff53f44,
0xbfc6bec8,0xbe493ffb,0xbfa2bffb,0xbfffbec8,0x4000,0xbfb54000,0xc0000000,0xbfb50000,0xc000,0x3fb50000,0x40000000,0xbfb54000,
0x4000,0x3fb5c000,0xc0000000,0x3fb50000,0xc000,0xbfb50000,0x40000000,0x3fb5c000,0xbfa2bfb5,0x3e49bfb5,0x3fc6bfb5,0x3fffbfb5,
0x3f713fd5,0xbff53f8e,0xbfe23f8e,0x3f15bfd5,0xbf15bfed,0xbf713fed,0x3ff5bf44,0xbfe23f44,0x3e493ffb,0x3fc6bec8,0xbfff3ec8,0xbfa23ffb,
0x3ffb0000,0x3f8e0000,0xbec84000,0xbfd54000,0xbfd5bf44,0x3ffbbfed,0x3f8ebfed,0x3ec83f44,0x3f8e3fb5,0x3ec8bfb5,0xbfd53fb5,0x3ffbbfb5,
0xbec8bfed,0xbfd53f44,0x3ffbbf44,0x3f8ebfed,0xbfe23fb5,0xbff53fb5,0xbf71bfb5,0x3f15bfb5,0x3fffbec8,0xbfc63ffb,0xbe493ffb,0xbfa23ec8,
0xbfc6bf44,0x3e493f44,0x3fa2bfed,0xbfff3fed,0x3f153fd5,0x3fe2bf8e,0xbff53f8e,0xbf713fd5,0x3f44c000,0x3fedc000,0x3fed0000,0x3f440000,
0xbfed3fb5,0x3f44bfb5,0xbf44bfb5,0x3fedbfb5,0x3fed0000,0xbf440000,0xbf444000,0x3fedc000,0xbf44bfb5,0xbfed3fb5,0x3fedbfb5,0x3f44bfb5,
0x3f153fb5,0xbf713fb5,0xbff53fb5,0xbfe23fb5,0x3fa2bffb,0x3e493ec8,0x3fc63ec8,0xbfff3ffb,0xbfff3f44,0x3fa2bf44,0x3e49bfed,0xbfc63fed,
0x3f713f8e,0x3ff5bfd5,0xbfe23fd5,0xbf153f8e,0xbfd50000,0xbec80000,0x3f8ec000,0x3ffbc000,0xbec83fed,0xbf8e3f44,0xbffb3f44,0x3fd5bfed,
0x3ffbbfb5,0xbfd53fb5,0x3ec83fb5,0x3f8ebfb5,0xbf8ebf44,0xbffb3fed,0x3fd5bfed,0x3ec8bf44,0x3fffbfb5,0x3fc6bfb5,0x3e493fb5,0xbfa23fb5,
0xbf15bf8e,0x3fe2bfd5,0x3ff5bfd5,0xbf713f8e,0xbfe23fed,0x3ff5bfed,0xbf71bf44,0xbf153f44,0x3fa23ec8,0x3fffbffb,0xbfc63ffb,0xbe493ec8,
0xc0004000,0xbfb54000,0x0,0x3fb50000,0xc0004000,0x3fb50000,0x0,0x3fb5c000,0xc0004000,0x3fb5c000,0x0,0xbfb50000,
0xc0004000,0xbfb50000,0x0,0xbfb54000,0x3fc6bfb5,0x3fffbfb5,0x3fa2bfb5,0xbe49bfb5,0x3fe2bfd5,0xbf15bf8e,0x3f71bf8e,0xbff53fd5,
0x3ff5bfed,0xbfe23fed,0x3f15bf44,0x3f713f44,0x3fffbffb,0x3fa23ec8,0x3e49bec8,0x3fc6bffb,0xbec80000,0xbfd50000,0xbffb4000,0xbf8e4000,
0xbf8e3f44,0xbec83fed,0xbfd53fed,0x3ffbbf44,0xbfd53fb5,0x3ffbbfb5,0xbf8e3fb5,0xbec8bfb5,0xbffb3fed,0xbf8ebf44,0xbec83f44,0xbfd53fed,
0xbf713fb5,0x3f153fb5,0x3fe2bfb5,0x3ff5bfb5,0x3e493ec8,0x3fa2bffb,0x3fffbffb,0xbfc6bec8,0x3fa2bf44,0xbfff3f44,0x3fc6bfed,0xbe493fed,
0x3ff5bfd5,0x3f713f8e,0x3f15bf8e,0x3fe2bfd5,0x3fedc000,0x3f44c000,0xbf440000,0xbfed0000,0x3f44bfb5,0xbfed3fb5,0xbfed3fb5,0x3f443fb5,
0xbf440000,0x3fed0000,0xbfed4000,0x3f44c000,0xbfed3fb5,0xbf44bfb5,0xbf443fb5,0xbfed3fb5,0xbff53fb5,0xbfe23fb5,0xbf153fb5,0x3f713fb5,
0xbfc63ffb,0x3fffbec8,0x3fa2bec8,0x3e49bffb,0x3e493f44,0xbfc6bf44,0x3fffbfed,0xbfa23fed,0x3fe2bf8e,0x3f153fd5,0x3f71bfd5,0x3ff5bf8e,
0x3f8e0000,0x3ffb0000,0x3fd5c000,0x3ec8c000,0x3ffbbfed,0xbfd5bf44,0xbec8bf44,0xbf8e3fed,0x3ec8bfb5,0x3f8e3fb5,0xbffb3fb5,0x3fd5bfb5,
0xbfd53f44,0xbec8bfed,0xbf8e3fed,0xbffb3f44,0x3e49bfb5,0xbfa2bfb5,0xbfff3fb5,0xbfc63fb5,0xbff53f8e,0x3f713fd5,0xbf153fd5,0x3fe2bf8e,
0xbf713fed,0xbf15bfed,0x3fe2bf44,0xbff53f44,0x3fc6bec8,0x3e493ffb,0x3fa2bffb,0x3fffbec8,0x4000,0x3fb54000,0x40000000,0x3fb50000,
0xc000,0xbfb50000,0xc0000000,0x3fb54000,0x4000,0xbfb5c000,0x40000000,0xbfb50000,0xc000,0x3fb50000,0xc0000000,0xbfb5c000,
0x3fa2bfb5,0xbe49bfb5,0xbfc6bfb5,0xbfffbfb5,0xbf713fd5,0x3ff53f8e,0x3fe23f8e,0xbf15bfd5,0x3f15bfed,0x3f713fed,0xbff5bf44,0x3fe23f44,
0xbe493ffb,0xbfc6bec8,0x3fff3ec8,0x3fa23ffb,0xbffb0000,0xbf8e0000,0x3ec84000,0x3fd54000,0x3fd5bf44,0xbffbbfed,0xbf8ebfed,0xbec83f44,
0xbf8e3fb5,0xbec8bfb5,0x3fd53fb5,0xbffbbfb5,0x3ec8bfed,0x3fd53f44,0xbffbbf44,0xbf8ebfed,0x3fe23fb5,0x3ff53fb5,0x3f71bfb5,0xbf15bfb5,
0xbfffbec8,0x3fc63ffb,0x3e493ffb,0x3fa23ec8,0x3fc6bf44,0xbe493f44,0xbfa2bfed,0x3fff3fed,0xbf153fd5,0xbfe2bf8e,0x3ff53f8e,0x3f713fd5,
0xbf44c000,0xbfedc000,0xbfed0000,0xbf440000,0x3fed3fb5,0xbf44bfb5,0x3f44bfb5,0xbfedbfb5,0xbfed0000,0x3f440000,0x3f444000,0xbfedc000,
0x3f44bfb5,0x3fed3fb5,0xbfedbfb5,0xbf44bfb5,0xbf153fb5,0x3f713fb5,0x3ff53fb5,0x3fe23fb5,0xbfa2bffb,0xbe493ec8,0xbfc63ec8,0x3fff3ffb,
0x3fff3f44,0xbfa2bf44,0xbe49bfed,0x3fc63fed,0xbf713f8e,0xbff5bfd5,0x3fe23fd5,0x3f153f8e,0x3fd50000,0x3ec80000,0xbf8ec000,0xbffbc000,
0x3ec83fed,0x3f8e3f44,0x3ffb3f44,0xbfd5bfed,0xbffbbfb5,0x3fd53fb5,0xbec83fb5,0xbf8ebfb5,0x3f8ebf44,0x3ffb3fed,0xbfd5bfed,0xbec8bf44,
0xbfffbfb5,0xbfc6bfb5,0xbe493fb5,0x3fa23fb5,0x3f15bf8e,0xbfe2bfd5,0xbff5bfd5,0x3f713f8e,0x3fe23fed,0xbff5bfed,0x3f71bf44,0x3f153f44,
0xbfa23ec8,0xbfffbffb,0x3fc63ffb,0x3e493ec8,0x80003f80,0x3f800000,0x80003f80,0x3f800000,0x80003f80,0x3f800000,0x80003f80,0x3f800000,
0x80003f80,0x3f800000,0x80003f80,0x3f800000,0x80003f80,0x3f800000,0x80003f80,0x3f800000,0x80003f80,0x3f800000,0x8000bf80,0xbf800000,
0x3f353f35,0x3f35bf35,0xbf35bf35,0xbf353f35,0x3f800000,0xbf80,0xbf800000,0x3f80,0x3f35bf35,0xbf35bf35,0xbf353f35,0x3f353f35,
0x80003f80,0x3f800000,0x80003f80,0x3f800000,0x3f800000,0xbf80,0x3f800000,0xbf80,0x8000bf80,0xbf800000,0x8000bf80,0xbf800000,
0xbf800000,0x3f80,0xbf800000,0x3f80,0x80003f80,0x3f800000,0x8000bf80,0xbf800000,0x3f35bf35,0xbf35bf35,0xbf353f35,0x3f353f35,
0xbf800000,0x3f80,0x3f800000,0xbf80,0x3f353f35,0x3f35bf35,0xbf35bf35,0xbf353f35,0x80003f80,0x3f800000,0x80003f80,0x3f800000,
0x8000bf80,0xbf800000,0x8000bf80,0xbf800000,0x80003f80,0x3f800000,0x80003f80,0x3f800000,0x8000bf80,0xbf800000,0x8000bf80,0xbf800000,
0x80003f80,0x3f800000,0x8000bf80,0xbf800000,0xbf35bf35,0xbf353f35,0x3f353f35,0x3f35bf35,0x3f800000,0xbf80,0xbf800000,0x3f80,
0xbf353f35,0x3f353f35,0x3f35bf35,0xbf35bf35,0x80003f80,0x3f800000,0x80003f80,0x3f800000,0xbf800000,0x3f80,0xbf800000,0x3f80,
0x8000bf80,0xbf800000,0x8000bf80,0xbf800000,0x3f800000,0xbf80,0x3f800000,0xbf80,0x80003f80,0x3f800000,0x8000bf80,0xbf800000,
0xbf353f35,0x3f353f35,0x3f35bf35,0xbf35bf35,0xbf800000,0x3f80,0x3f800000,0xbf80,0xbf35bf35,0xbf353f35,0x3f353f35,0x3f35bf35,
0x3f803f80,0x80008000,0x80008000,0xbf80bf80,0x3f803f80,0x80008000,0x80008000,0xbf80bf80,0x3f803f80,0x80008000,0x80008000,0xbf80bf80,
0x3f803f80,0x80008000,0x80008000,0xbf80bf80,0x3f353f80,0x3f358000,0x3f358000,0xbf35bf80,0xbf350000,0x3f353f80,0x3f353f80,0x3f358000,
0xbf35bf80,0xbf358000,0xbf358000,0x3f353f80,0x3f350000,0xbf35bf80,0xbf35bf80,0xbf358000,0x3f80,0x3f808000,0x3f808000,0x8000bf80,
0xbf80,0xbf808000,0xbf808000,0x80003f80,0x3f80,0x3f808000,0x3f808000,0x8000bf80,0xbf80,0xbf808000,0xbf808000,0x80003f80,
0xbf353f80,0x3f358000,0x3f358000,0x3f35bf80,0x3f350000,0x3f35bf80,0x3f35bf80,0xbf358000,0x3f35bf80,0xbf358000,0xbf358000,0xbf353f80,
0xbf350000,0xbf353f80,0xbf353f80,0x3f358000,0xbf803f80,0x80008000,0x80008000,0x3f80bf80,0xbf803f80,0x80008000,0x80008000,0x3f80bf80,
0xbf803f80,0x80008000,0x80008000,0x3f80bf80,0xbf803f80,0x80008000,0x80008000,0x3f80bf80,0xbf353f80,0xbf358000,0xbf358000,0x3f35bf80,
0x3f350000,0xbf353f80,0xbf353f80,0xbf358000,0x3f35bf80,0x3f358000,0x3f358000,0xbf353f80,0xbf350000,0x3f35bf80,0x3f35bf80,0x3f358000,
0x3f80,0xbf808000,0xbf808000,0x8000bf80,0xbf80,0x3f808000,0x3f808000,0x80003f80,0x3f80,0xbf808000,0xbf808000,0x8000bf80,
0xbf80,0x3f808000,0x3f808000,0x80003f80,0x3f353f80,0xbf358000,0xbf358000,0xbf35bf80,0xbf350000,0xbf35bf80,0xbf35bf80,0x3f358000,
0xbf35bf80,0x3f358000,0x3f358000,0x3f353f80,0x3f350000,0x3f353f80,0x3f353f80,0xbf358000,0x3f800000,0x0,0x3f800000,0x0,
0x3f800000,0x0,0x3f800000,0x0,0x3f800000,0x0,0x3f800000,0x0,0x3f800000,0x0,0x3f800000,0x0,
0x3f800000,0x0,0x3f7fb10f,0xbd48fb30,0x3f7ec46d,0xbdc8bd36,0x3f7d3aac,0xbe164083,0x3f7b14be,0xbe47c5c2,0x3f7853f8,0xbe78cfcc,
0x3f74fa0b,0xbe94a031,0x3f710908,0xbeac7cd4,0x3f800000,0x0,0x3f7ec46d,0xbdc8bd36,0x3f7b14be,0xbe47c5c2,0x3f74fa0b,0xbe94a031,
0x3f6c835e,0xbec3ef15,0x3f61c598,0xbef15aea,0x3f54db31,0xbf0e39da,0x3f45e403,0xbf226799,0x3f800000,0x0,0x3f7d3aac,0xbe164083,
0x3f74fa0b,0xbe94a031,0x3f676bd8,0xbedae880,0x3f54db31,0xbf0e39da,0x3f3daef9,0xbf2beb4a,0x3f226799,0xbf45e403,0x3f039c3d,0xbf5b941a,
0x3f800000,0x0,0x3f7b14be,0xbe47c5c2,0x3f6c835e,0xbec3ef15,0x3f54db31,0xbf0e39da,0x3f3504f3,0xbf3504f3,0x3f0e39da,0xbf54db31,
0x3ec3ef15,0xbf6c835e,0x3e47c5c2,0xbf7b14be,0x3f800000,0x0,0x3f7853f8,0xbe78cfcc,0x3f61c598,0xbef15aea,0x3f3daef9,0xbf2beb4a,
0x3f0e39da,0xbf54db31,0x3eac7cd4,0xbf710908,0x3dc8bd36,0xbf7ec46d,0xbe164083,0xbf7d3aac,0x3f800000,0x0,0x3f74fa0b,0xbe94a031,
0x3f54db31,0xbf0e39da,0x3f226799,0xbf45e403,0x3ec3ef15,0xbf6c835e,0x3dc8bd36,0xbf7ec46d,0xbe47c5c2,0xbf7b14be,0xbef15aea,0xbf61c598,
0x3f800000,0x0,0x3f710908,0xbeac7cd4,0x3f45e403,0xbf226799,0x3f039c3d,0xbf5b941a,0x3e47c5c2,0xbf7b14be,0xbe164083,0xbf7d3aac,
0xbef15aea,0xbf61c598,0xbf3daef9,0xbf2beb4a,0x3f800000,0x0,0x3f800000,0x0,0x3f800000,0x0,0x3f800000,0x0,
0x3f800000,0x0,0x3f800000,0x0,0x3f800000,0x0,0x3f800000,0x0,0x3f6c835e,0xbec3ef15,0x3f676bd8,0xbedae880,
0x3f61c598,0xbef15aea,0x3f5b941a,0xbf039c3d,0x3f54db31,0xbf0e39da,0x3f4d9f02,0xbf187fc0,0x3f45e403,0xbf226799,0x3f3daef9,0xbf2beb4a,
0x3f3504f3,0xbf3504f3,0x3f226799,0xbf45e403,0x3f0e39da,0xbf54db31,0x3ef15aea,0xbf61c598,0x3ec3ef15,0xbf6c835e,0x3e94a031,0xbf74fa0b,
0x3e47c5c2,0xbf7b14be,0x3dc8bd36,0xbf7ec46d,0x3ec3ef15,0xbf6c835e,0x3e78cfcc,0xbf7853f8,0x3dc8bd36,0xbf7ec46d,0xbd48fb30,0xbf7fb10f,
0xbe47c5c2,0xbf7b14be,0xbeac7cd4,0xbf710908,0xbef15aea,0xbf61c598,0xbf187fc0,0xbf4d9f02,0x0,0xbf800000,0xbe47c5c2,0xbf7b14be,
0xbec3ef15,0xbf6c835e,0xbf0e39da,0xbf54db31,0xbf3504f3,0xbf3504f3,0xbf54db31,0xbf0e39da,0xbf6c835e,0xbec3ef15,0xbf7b14be,0xbe47c5c2,
0xbec3ef15,0xbf6c835e,0xbf187fc0,0xbf4d9f02,0xbf45e403,0xbf226799,0xbf676bd8,0xbedae880,0xbf7b14be,0xbe47c5c2,0xbf7fb10f,0x3d48fb30,
0xbf74fa0b,0x3e94a031,0xbf5b941a,0x3f039c3d,0xbf3504f3,0xbf3504f3,0xbf61c598,0xbef15aea,0xbf7b14be,0xbe47c5c2,0xbf7ec46d,0x3dc8bd36,
0xbf6c835e,0x3ec3ef15,0xbf45e403,0x3f226799,0xbf0e39da,0x3f54db31,0xbe94a031,0x3f74fa0b,0xbf6c835e,0xbec3ef15,0xbf7fb10f,0xbd48fb30,
0xbf74fa0b,0x3e94a031,0xbf4d9f02,0x3f187fc0,0xbf0e39da,0x3f54db31,0xbe78cfcc,0x3f7853f8,0x3dc8bd36,0x3f7ec46d,0x3edae880,0x3f676bd8,
0x80003f80,0x3f800000,0x3f800000,0xbf80,0x3ec43f6d,0x3f6dbec4,0x3f6dbec4,0xbec4bf6d,0x3f353f35,0x3f35bf35,0x3f35bf35,0xbf35bf35,
0x3f6d3ec4,0x3ec4bf6d,0x3ec4bf6d,0xbf6dbec4,0x80003f80,0x3f800000,0xbf800000,0x3f80,0x3f6d3ec4,0x3ec4bf6d,0xbec43f6d,0x3f6d3ec4,
0x3f35bf35,0xbf35bf35,0x3f353f35,0x3f35bf35,0xbec4bf6d,0xbf6d3ec4,0x3f6dbec4,0xbec4bf6d,0x80003f80,0x3f800000,0x3f800000,0xbf80,
0x3f6dbec4,0xbec4bf6d,0xbec4bf6d,0xbf6d3ec4,0xbf35bf35,0xbf353f35,0xbf353f35,0x3f353f35,0xbec43f6d,0x3f6d3ec4,0x3f6d3ec4,0x3ec4bf6d,
0x80003f80,0x3f800000,0xbf800000,0x3f80,0x3ec4bf6d,0xbf6dbec4,0x3f6d3ec4,0x3ec4bf6d,0xbf353f35,0x3f353f35,0xbf35bf35,0xbf353f35,
0x3f6dbec4,0xbec4bf6d,0x3ec43f6d,0x3f6dbec4,0x80003f80,0x3f800000,0x3f800000,0xbf80,0xbec4bf6d,0xbf6d3ec4,0xbf6d3ec4,0x3ec43f6d,
0x3f353f35,0x3f35bf35,0x3f35bf35,0xbf35bf35,0xbf6dbec4,0xbec43f6d,0xbec43f6d,0x3f6d3ec4,0x80003f80,0x3f800000,0xbf800000,0x3f80,
0xbf6dbec4,0xbec43f6d,0x3ec4bf6d,0xbf6dbec4,0x3f35bf35,0xbf35bf35,0x3f353f35,0x3f35bf35,0x3ec43f6d,0x3f6dbec4,0xbf6d3ec4,0x3ec43f6d,
0x80003f80,0x3f800000,0x3f800000,0xbf80,0xbf6d3ec4,0x3ec43f6d,0x3ec43f6d,0x3f6dbec4,0xbf35bf35,0xbf353f35,0xbf353f35,0x3f353f35,
0x3ec4bf6d,0xbf6dbec4,0xbf6dbec4,0xbec43f6d,0x80003f80,0x3f800000,0xbf800000,0x3f80,0xbec43f6d,0x3f6d3ec4,0xbf6dbec4,0xbec43f6d,
0xbf353f35,0x3f353f35,0xbf35bf35,0xbf353f35,0xbf6d3ec4,0x3ec43f6d,0xbec4bf6d,0xbf6d3ec4,0x3f803f80,0x80008000,0x80008000,0xbf80bf80,
0x3f803f80,0x80008000,0x80008000,0xbf80bf80,0x3f803f80,0x80008000,0x80008000,0xbf80bf80,0x3f803f80,0x80008000,0x80008000,0xbf80bf80,
0x3ec43f6d,0x3f6d3ec4,0x3f6d3ec4,0xbec4bf6d,0xbf6dbec4,0x3ec43f6d,0x3ec43f6d,0x3f6d3ec4,0xbec4bf6d,0xbf6dbec4,0xbf6dbec4,0x3ec43f6d,
0x3f6d3ec4,0xbec4bf6d,0xbec4bf6d,0xbf6dbec4,0xbf353f35,0x3f353f35,0x3f353f35,0x3f35bf35,0x3f35bf35,0xbf35bf35,0xbf35bf35,0xbf353f35,
0xbf353f35,0x3f353f35,0x3f353f35,0x3f35bf35,0x3f35bf35,0xbf35bf35,0xbf35bf35,0xbf353f35,0xbf6d3ec4,0xbec43f6d,0xbec43f6d,0x3f6dbec4,
0xbec43f6d,0x3f6dbec4,0x3f6dbec4,0x3ec4bf6d,0x3f6dbec4,0x3ec4bf6d,0x3ec4bf6d,0xbf6d3ec4,0x3ec4bf6d,0xbf6d3ec4,0xbf6d3ec4,0xbec43f6d,
0x0,0xbf803f80,0xbf803f80,0x80008000,0x0,0xbf803f80,0xbf803f80,0x80008000,0x0,0xbf803f80,0xbf803f80,0x80008000,
0x0,0xbf803f80,0xbf803f80,0x80008000,0x3f6dbec4,0xbec43f6d,0xbec43f6d,0xbf6d3ec4,0x3ec4bf6d,0x3f6dbec4,0x3f6dbec4,0xbec43f6d,
0xbf6d3ec4,0x3ec4bf6d,0x3ec4bf6d,0x3f6dbec4,0xbec43f6d,0xbf6d3ec4,0xbf6d3ec4,0x3ec4bf6d,0x3f35bf35,0x3f353f35,0x3f353f35,0xbf353f35,
0xbf353f35,0xbf35bf35,0xbf35bf35,0x3f35bf35,0x3f35bf35,0x3f353f35,0x3f353f35,0xbf353f35,0xbf353f35,0xbf35bf35,0xbf35bf35,0x3f35bf35,
0xbec4bf6d,0x3f6d3ec4,0x3f6d3ec4,0x3ec43f6d,0x3f6d3ec4,0x3ec43f6d,0x3ec43f6d,0xbf6dbec4,0x3ec43f6d,0xbf6dbec4,0xbf6dbec4,0xbec4bf6d,
0xbf6dbec4,0xbec4bf6d,0xbec4bf6d,0x3f6d3ec4,0x3f800000,0x0,0x3f7fec43,0xbcc90ab0,0x3f7fb10f,0xbd48fb30,0x3f7f4e6d,0xbd96a905,
0x3f7ec46d,0xbdc8bd36,0x3f7e1324,0xbdfab273,0x3f7d3aac,0xbe164083,0x3f7c3b28,0xbe2f10a2,0x3f800000,0x0,0x3f7f4e6d,0xbd96a905,
0x3f7d3aac,0xbe164083,0x3f79c79d,0xbe605c13,0x3f74fa0b,0xbe94a031,0x3f6ed89e,0xbeb8442a,0x3f676bd8,0xbedae880,0x3f5ebe05,0xbefc5d27,
0x3f800000,0x0,0x3f7e1324,0xbdfab273,0x3f7853f8,0xbe78cfcc,0x3f6ed89e,0xbeb8442a,0x3f61c598,0xbef15aea,0x3f514d3d,0xbf13682a,
0x3f3daef9,0xbf2beb4a,0x3f273656,0xbf41d870,0x3f800000,0x0,0x3f7c3b28,0xbe2f10a2,0x3f710908,0xbeac7cd4,0x3f5ebe05,0xbefc5d27,
0x3f45e403,0xbf226799,0x3f273656,0xbf41d870,0x3f039c3d,0xbf5b941a,0x3eb8442a,0xbf6ed89e,0x3f800000,0x0,0x3f79c79d,0xbe605c13,
0x3f676bd8,0xbedae880,0x3f49d112,0xbf1d7fd1,0x3f226799,0xbf45e403,0x3ee63375,0xbf64aa59,0x3e78cfcc,0xbf7853f8,0x3cc90ab0,0xbf7fec43,
0x3f800000,0x0,0x3f76ba07,0xbe888e93,0x3f5b941a,0xbf039c3d,0x3f3085bb,0xbf396842,0x3ef15aea,0xbf61c598,0x3e605c13,0xbf79c79d,
0xbd48fb30,0xbf7fb10f,0xbea09ae5,0xbf731447,0x3f800000,0x0,0x3f731447,0xbea09ae5,0x3f4d9f02,0xbf187fc0,0x3f13682a,0xbf514d3d,
0x3e94a031,0xbf74fa0b,0xbcc90ab0,0xbf7fec43,0xbeac7cd4,0xbf710908,0xbf1d7fd1,0xbf49d112,0x3f800000,0x0,0x3f6ed89e,0xbeb8442a,
0x3f3daef9,0xbf2beb4a,0x3ee63375,0xbf64aa59,0x3dc8bd36,0xbf7ec46d,0xbe888e93,0xbf76ba07,0xbf187fc0,0xbf4d9f02,0xbf584853,0xbf08f59b,
0x3f7b14be,0xbe47c5c2,0x3f79c79d,0xbe605c13,0x3f7853f8,0xbe78cfcc,0x3f76ba07,0xbe888e93,0x3f74fa0b,0xbe94a031,0x3f731447,0xbea09ae5,
0x3f710908,0xbeac7cd4,0x3f6ed89e,0xbeb8442a,0x3f54db31,0xbf0e39da,0x3f49d112,0xbf1d7fd1,0x3f3daef9,0xbf2beb4a,0x3f3085bb,0xbf396842,
0x3f226799,0xbf45e403,0x3f13682a,0xbf514d3d,0x3f039c3d,0xbf5b941a,0x3ee63375,0xbf64aa59,0x3f0e39da,0xbf54db31,0x3ee63375,0xbf64aa59,
0x3eac7cd4,0xbf710908,0x3e605c13,0xbf79c79d,0x3dc8bd36,0xbf7ec46d,0xbcc90ab0,0xbf7fec43,0xbe164083,0xbf7d3aac,0xbe888e93,0xbf76ba07,
0x3e47c5c2,0xbf7b14be,0x3cc90ab0,0xbf7fec43,0xbe164083,0xbf7d3aac,0xbea09ae5,0xbf731447,0xbef15aea,0xbf61c598,0xbf1d7fd1,0xbf49d112,
0xbf3daef9,0xbf2beb4a,0xbf584853,0xbf08f59b,0xbe47c5c2,0xbf7b14be,0xbecf7bca,0xbf6a09a7,0xbf187fc0,0xbf4d9f02,0xbf41d870,0xbf273656,
0xbf61c598,0xbef15aea,0xbf76ba07,0xbe888e93,0xbf7fb10f,0xbd48fb30,0xbf7c3b28,0x3e2f10a2,0xbf0e39da,0xbf54db31,0xbf41d870,0xbf273656,
0xbf676bd8,0xbedae880,0xbf7c3b28,0xbe2f10a2,0xbf7ec46d,0x3dc8bd36,0xbf6ed89e,0x3eb8442a,0xbf4d9f02,0x3f187fc0,0xbf1d7fd1,0x3f49d112,
0xbf54db31,0xbf0e39da,0xbf76ba07,0xbe888e93,0xbf7fb10f,0x3d48fb30,0xbf6ed89e,0x3eb8442a,0xbf45e403,0x3f226799,0xbf08f59b,0x3f584853,
0xbe78cfcc,0x3f7853f8,0x3d96a905,0x3f7f4e6d,0xbf7b14be,0xbe47c5c2,0xbf7c3b28,0x3e2f10a2,0xbf5b941a,0x3f039c3d,0xbf1d7fd1,0x3f49d112,
0xbe94a031,0x3f74fa0b,0x3d96a905,0x3f7f4e6d,0x3edae880,0x3f676bd8,0x3f396842,0x3f3085bb,0x80003f80,0x80003f80,0x80003f80,0x80003f80,
0x80003f80,0x80003f80,0x80003f80,0x80003f80,0x80003f80,0x80003f80,0x80003f80,0x80003f80,0x80003f80,0x80003f80,0x80003f80,0x80003f80,
0x3f800000,0x3f800000,0x3f800000,0x3f800000,0x3f800000,0x3f800000,0x3f800000,0x3f800000,0x3f800000,0x3f800000,0x3f800000,0x3f800000,
0x3f800000,0x3f800000,0x3f800000,0x3f800000,0x80003f80,0x3f353f35,0x80003f80,0x3f353f35,0x3f800000,0x3f35bf35,0x3f800000,0x3f35bf35,
0x8000bf80,0xbf35bf35,0x8000bf80,0xbf35bf35,0xbf800000,0xbf353f35,0xbf800000,0xbf353f35,0x3f800000,0x3f35bf35,0x3f800000,0x3f35bf35,
0xbf80,0xbf35bf35,0xbf80,0xbf35bf35,0xbf800000,0xbf353f35,0xbf800000,0xbf353f35,0x3f80,0x3f353f35,0x3f80,0x3f353f35,
0x80003f80,0x3f800000,0x80003f80,0x3f800000,0x8000bf80,0xbf800000,0x8000bf80,0xbf800000,0x80003f80,0x3f800000,0x80003f80,0x3f800000,
0x8000bf80,0xbf800000,0x8000bf80,0xbf800000,0x3f800000,0xbf80,0x3f800000,0xbf80,0xbf800000,0x3f80,0xbf800000,0x3f80,
0x3f800000,0xbf80,0x3f800000,0xbf80,0xbf800000,0x3f80,0xbf800000,0x3f80,0x80003f80,0x3f35bf35,0x80003f80,0x3f35bf35,
0xbf800000,0x3f353f35,0xbf800000,0x3f353f35,0x8000bf80,0xbf353f35,0x8000bf80,0xbf353f35,0x3f800000,0xbf35bf35,0x3f800000,0xbf35bf35,
0x3f800000,0xbf35bf35,0x3f800000,0xbf35bf35,0x3f80,0x3f35bf35,0x3f80,0x3f35bf35,0xbf800000,0x3f353f35,0xbf800000,0x3f353f35,
0xbf80,0xbf353f35,0xbf80,0xbf353f35,0x80003f80,0x3ec43f6d,0x8000bf80,0xbec4bf6d,0x3f353f35,0x3f6d3ec4,0xbf35bf35,0xbf6dbec4,
0x3f800000,0x3f6dbec4,0xbf800000,0xbf6d3ec4,0x3f35bf35,0x3ec4bf6d,0xbf353f35,0xbec43f6d,0x3f800000,0x3f6dbec4,0xbf800000,0xbf6d3ec4,
0x3f35bf35,0x3ec4bf6d,0xbf353f35,0xbec43f6d,0xbf80,0xbec4bf6d,0x3f80,0x3ec43f6d,0xbf35bf35,0xbf6dbec4,0x3f353f35,0x3f6d3ec4,
0x80003f80,0x3f6d3ec4,0x8000bf80,0xbf6dbec4,0x3f35bf35,0xbec4bf6d,0xbf353f35,0x3ec43f6d,0xbf800000,0xbec43f6d,0x3f800000,0x3ec4bf6d,
0x3f353f35,0x3f6dbec4,0xbf35bf35,0xbf6d3ec4,0x3f800000,0x3ec4bf6d,0xbf800000,0xbec43f6d,0xbf35bf35,0xbf6d3ec4,0x3f353f35,0x3f6dbec4,
0x3f80,0x3f6d3ec4,0xbf80,0xbf6dbec4,0x3f35bf35,0xbec4bf6d,0xbf353f35,0x3ec43f6d,0x80003f80,0x3f6dbec4,0x8000bf80,0xbf6d3ec4,
0xbf35bf35,0xbec43f6d,0x3f353f35,0x3ec4bf6d,0x3f800000,0xbec4bf6d,0xbf800000,0x3ec43f6d,0xbf353f35,0x3f6d3ec4,0x3f35bf35,0xbf6dbec4,
0x3f800000,0xbec4bf6d,0xbf800000,0x3ec43f6d,0xbf353f35,0x3f6d3ec4,0x3f35bf35,0xbf6dbec4,0xbf80,0xbf6d3ec4,0x3f80,0x3f6dbec4,
0x3f353f35,0x3ec4bf6d,0xbf35bf35,0xbec43f6d,0x80003f80,0x3ec4bf6d,0x8000bf80,0xbec43f6d,0xbf353f35,0x3f6dbec4,0x3f35bf35,0xbf6d3ec4,
0xbf800000,0x3f6d3ec4,0x3f800000,0xbf6dbec4,0xbf35bf35,0x3ec43f6d,0x3f353f35,0xbec4bf6d,0x3f800000,0xbf6dbec4,0xbf800000,0x3f6d3ec4,
0x3f353f35,0xbec4bf6d,0xbf35bf35,0x3ec43f6d,0x3f80,0x3ec4bf6d,0xbf80,0xbec43f6d,0xbf353f35,0x3f6dbec4,0x3f35bf35,0xbf6d3ec4,
0x80003f80,0x8000bf80,0x80003f80,0x8000bf80,0x80003f80,0x8000bf80,0x80003f80,0x8000bf80,0x80003f80,0x8000bf80,0x80003f80,0x8000bf80,
0x80003f80,0x8000bf80,0x80003f80,0x8000bf80,0x3f800000,0xbf800000,0x3f800000,0xbf800000,0x3f800000,0xbf800000,0x3f800000,0xbf800000,
0x3f800000,0xbf800000,0x3f800000,0xbf800000,0x3f800000,0xbf800000,0x3f800000,0xbf800000,0x80003f80,0xbf35bf35,0x80003f80,0xbf35bf35,
0x3f800000,0xbf353f35,0x3f800000,0xbf353f35,0x8000bf80,0x3f353f35,0x8000bf80,0x3f353f35,0xbf800000,0x3f35bf35,0xbf800000,0x3f35bf35,
0x3f800000,0xbf353f35,0x3f800000,0xbf353f35,0xbf80,0x3f353f35,0xbf80,0x3f353f35,0xbf800000,0x3f35bf35,0xbf800000,0x3f35bf35,
0x3f80,0xbf35bf35,0x3f80,0xbf35bf35,0x80003f80,0xbf800000,0x80003f80,0xbf800000,0x8000bf80,0x3f800000,0x8000bf80,0x3f800000,
0x80003f80,0xbf800000,0x80003f80,0xbf800000,0x8000bf80,0x3f800000,0x8000bf80,0x3f800000,0x3f800000,0x3f80,0x3f800000,0x3f80,
0xbf800000,0xbf80,0xbf800000,0xbf80,0x3f800000,0x3f80,0x3f800000,0x3f80,0xbf800000,0xbf80,0xbf800000,0xbf80,
0x80003f80,0xbf353f35,0x80003f80,0xbf353f35,0xbf800000,0xbf35bf35,0xbf800000,0xbf35bf35,0x8000bf80,0x3f35bf35,0x8000bf80,0x3f35bf35,
0x3f800000,0x3f353f35,0x3f800000,0x3f353f35,0x3f800000,0x3f353f35,0x3f800000,0x3f353f35,0x3f80,0xbf353f35,0x3f80,0xbf353f35,
0xbf800000,0xbf35bf35,0xbf800000,0xbf35bf35,0xbf80,0x3f35bf35,0xbf80,0x3f35bf35,0x80003f80,0xbec4bf6d,0x8000bf80,0x3ec43f6d,
0x3f353f35,0xbf6dbec4,0xbf35bf35,0x3f6d3ec4,0x3f800000,0xbf6d3ec4,0xbf800000,0x3f6dbec4,0x3f35bf35,0xbec43f6d,0xbf353f35,0x3ec4bf6d,
0x3f800000,0xbf6d3ec4,0xbf800000,0x3f6dbec4,0x3f35bf35,0xbec43f6d,0xbf353f35,0x3ec4bf6d,0xbf80,0x3ec43f6d,0x3f80,0xbec4bf6d,
0xbf35bf35,0x3f6d3ec4,0x3f353f35,0xbf6dbec4,0x80003f80,0xbf6dbec4,0x8000bf80,0x3f6d3ec4,0x3f35bf35,0x3ec43f6d,0xbf353f35,0xbec4bf6d,
0xbf800000,0x3ec4bf6d,0x3f800000,0xbec43f6d,0x3f353f35,0xbf6d3ec4,0xbf35bf35,0x3f6dbec4,0x3f800000,0xbec43f6d,0xbf800000,0x3ec4bf6d,
0xbf35bf35,0x3f6dbec4,0x3f353f35,0xbf6d3ec4,0x3f80,0xbf6dbec4,0xbf80,0x3f6d3ec4,0x3f35bf35,0x3ec43f6d,0xbf353f35,0xbec4bf6d,
0x80003f80,0xbf6d3ec4,0x8000bf80,0x3f6dbec4,0xbf35bf35,0x3ec4bf6d,0x3f353f35,0xbec43f6d,0x3f800000,0x3ec43f6d,0xbf800000,0xbec4bf6d,
0xbf353f35,0xbf6dbec4,0x3f35bf35,0x3f6d3ec4,0x3f800000,0x3ec43f6d,0xbf800000,0xbec4bf6d,0xbf353f35,0xbf6dbec4,0x3f35bf35,0x3f6d3ec4,
0xbf80,0x3f6dbec4,0x3f80,0xbf6d3ec4,0x3f353f35,0xbec43f6d,0xbf35bf35,0x3ec4bf6d,0x80003f80,0xbec43f6d,0x8000bf80,0x3ec4bf6d,
0xbf353f35,0xbf6d3ec4,0x3f35bf35,0x3f6dbec4,0xbf800000,0xbf6dbec4,0x3f800000,0x3f6d3ec4,0xbf35bf35,0xbec4bf6d,0x3f353f35,0x3ec43f6d,
0x3f800000,0x3f6d3ec4,0xbf800000,0xbf6dbec4,0x3f353f35,0x3ec43f6d,0xbf35bf35,0xbec4bf6d,0x3f80,0xbec43f6d,0xbf80,0x3ec4bf6d,
0xbf353f35,0xbf6d3ec4,0x3f35bf35,0x3f6dbec4,
};
constexpr int TB_F = 0, TB_E = 512, TB_P2 = 1024;

enum { C_EP = 0, C_Z1 = 32, C_Z2 = 96, C_H3 = 128, C_U = 160, C_X = 288, C_TOTAL = 512 };
struct Scratch {
  unsigned cnt[C_TOTAL];
  uint32_t moda[8 * 2 * D_];
  uint32_t mod[4 * D_ + 256];
  uint32_t z1[120 * 5120];
  uint32_t z2[128 * 4800];
  uint8_t h3[32 * 18 * 4096];
  uint8_t u[72 * D_ * 128];
};
__device__ __align__(1024) Scratch g_s;

#define PF2 8
#define PF2K 16
#define HOLDA 5
#define GOAT 0
#define H3W 0
#define X1K 10
#define PEEK 1
#define PFF 2
#ifndef NV1
#define NV1 12
#endif
#ifndef NV2
#define NV2 20
#endif
#define GDEP 0
#define TRK0 50
#define W0N 3
#define TRKC 350
#define J2 6
#define MODPOS 2
#define LNM 0x30
constexpr int NB15 = 192 + 32 * __builtin_popcount(LNM);
#define NG1 2

#define FAILCNT(k) do {} while (0)
#define CK(k) do {} while (0)
#define CKX(k) do {} while (0)
#define TS(k) do {} while (0)
#define TSC(k) do {} while (0)
struct Maps { CUtensorMap z1, z2[2], w1a, w1b, h3, w2, wf[4], wm; };
struct Params {
  const __nv_bfloat16 *x, *c, *wmod;
  Scratch* s;
  const uint4* tab;
  const __nv_bfloat16 *wr, *wi, *w1, *w2, *b1, *b2;
  uint32_t* out;
};

__device__ __forceinline__ uint32_t smem_u32(const void* p) { return (uint32_t)__cvta_generic_to_shared(p); }
__device__ __forceinline__ void mbar_init(uint32_t b, int c) { asm volatile("mbarrier.init.shared::cta.b64 [%0], %1;" ::"r"(b), "r"(c)); }
__device__ __forceinline__ void mbar_expect(uint32_t b, int bytes) { asm volatile("mbarrier.arrive.expect_tx.shared::cta.b64 _, [%0], %1;" ::"r"(b), "r"(bytes) : "memory"); }
__device__ __forceinline__ void mbar_arrive(uint32_t b) { asm volatile("mbarrier.arrive.shared::cta.b64 _, [%0];" ::"r"(b) : "memory"); }
#define MBAR_WAIT(SEM)                                                                                                         \
  asm volatile("{\n.reg .pred p;\n.reg .u32 it;\nmov.u32 it, 0;\nW:\nmbarrier.try_wait.parity" SEM ".shared::cta.b64 p, [%0], %1;\n" \
               "@p bra.uni D;\nadd.u32 it, it, 1;\nsetp.lt.u32 p, it, 0x400000;\n@p bra.uni W;\ntrap;\nD:\n}" ::"r"(b), "r"(ph) : "memory")
__device__ __forceinline__ void mbar_wait(uint32_t b, int ph) { MBAR_WAIT(""); }
__device__ __forceinline__ uint32_t mbar_test(uint32_t b, int ph) {
  uint32_t ok;
  asm volatile("{\n.reg .pred p;\nmbarrier.test_wait.parity.shared::cta.b64 p, [%1], %2;\nselp.u32 %0, 1, 0, p;\n}\n" : "=r"(ok) : "r"(b), "r"(ph) : "memory");
  return ok;
}
__device__ __forceinline__ void tma2d(uint32_t dst, const CUtensorMap* m, int c0, int c1, uint32_t bar) {
  asm volatile("cp.async.bulk.tensor.2d.shared::cluster.global.mbarrier::complete_tx::bytes [%0], [%1, {%3, %4}], [%2];" ::"r"(dst), "l"(m), "r"(bar), "r"(c0), "r"(c1) : "memory");
}
__device__ __forceinline__ uint64_t pol_ef() { uint64_t p; asm("createpolicy.fractional.L2::evict_first.b64 %0, 1.0;" : "=l"(p)); return p; }
__device__ __forceinline__ void tma3d_ef(uint32_t dst, const CUtensorMap* m, int c1, int c2, uint32_t bar) {
  asm volatile("cp.async.bulk.tensor.3d.shared::cluster.global.mbarrier::complete_tx::bytes.L2::cache_hint [%0], [%1, {%3, %4, %5}], [%2], %6;" ::"r"(dst), "l"(m), "r"(bar), "r"(0), "r"(c1), "r"(c2), "l"(pol_ef()) : "memory");
}
__device__ __forceinline__ void tma4d_ef(uint32_t dst, const CUtensorMap* m, int c1, int c2, int c3, uint32_t bar) {
  asm volatile("cp.async.bulk.tensor.4d.shared::cluster.global.mbarrier::complete_tx::bytes.L2::cache_hint [%0], [%1, {%3, %7, %4, %5}], [%2], %6;" ::"r"(dst), "l"(m), "r"(bar), "r"(0), "r"(c2), "r"(c3), "l"(pol_ef()), "r"(c1) : "memory");
}
__device__ __forceinline__ void bulk_ld(uint32_t dst, const void* src, int bytes, uint32_t bar) {
  asm volatile("cp.async.bulk.shared::cluster.global.mbarrier::complete_tx::bytes [%0], [%1], %2, [%3];" ::"r"(dst), "l"(src), "r"(bytes), "r"(bar) : "memory");
}
__device__ __forceinline__ void bulk_st(void* dst, uint32_t src, int bytes) {
  asm volatile("cp.async.bulk.global.shared::cta.bulk_group [%0], [%1], %2;" ::"l"(dst), "r"(src), "r"(bytes) : "memory");
}
__device__ __forceinline__ void tma_st2d(const CUtensorMap* m, uint32_t src, int c0, int c1) {
  asm volatile("cp.async.bulk.tensor.2d.global.shared::cta.bulk_group [%0, {%2, %3}], [%1];" ::"l"(m), "r"(src), "r"(c0), "r"(c1) : "memory");
}
__device__ __forceinline__ void tma_st3d(const CUtensorMap* m, uint32_t src, int c0, int c1, int c2) {
  asm volatile("cp.async.bulk.tensor.3d.global.shared::cta.bulk_group [%0, {%2, %3, %4}], [%1];" ::"l"(m), "r"(src), "r"(c0), "r"(c1), "r"(c2) : "memory");
}
__device__ __forceinline__ void bulk_commit_wait_read() {
  asm volatile("cp.async.bulk.commit_group;" ::: "memory");
  asm volatile("cp.async.bulk.wait_group.read 0;" ::: "memory");
}
__device__ __forceinline__ void bulk_commit_wait() {
  asm volatile("cp.async.bulk.commit_group;" ::: "memory");
  asm volatile("cp.async.bulk.wait_group 0;" ::: "memory");
}
__device__ __forceinline__ void prefetch_l2(const void* p, int bytes) {
  asm volatile("cp.async.bulk.prefetch.L2.global [%0], %1;" ::"l"(p), "r"(bytes) : "memory");
}
__device__ __forceinline__ void wg_fence() { asm volatile("wgmma.fence.sync.aligned;" ::: "memory"); }
__device__ __forceinline__ void wg_commit() { asm volatile("wgmma.commit_group.sync.aligned;" ::: "memory"); }
template <int N> __device__ __forceinline__ void wg_wait() { asm volatile("wgmma.wait_group.sync.aligned %0;" ::"n"(N) : "memory"); }
template <int N> __device__ __forceinline__ void reg_fence(float (&d)[N]) {
#pragma unroll
  for (int i = 0; i < N; i++) asm volatile("" : "+f"(d[i])::"memory");
}
__device__ __forceinline__ void fence_async_smem() { asm volatile("fence.proxy.async.shared::cta;" ::: "memory"); }
__device__ __forceinline__ void fence_async_glb() { asm volatile("fence.proxy.async.global;" ::: "memory"); }
__device__ __forceinline__ uint32_t ld_rlx(const void* p) { uint32_t v; asm volatile("ld.relaxed.gpu.global.b32 %0, [%1];" : "=r"(v) : "l"(p) : "memory"); return v; }
__device__ __forceinline__ uint2 ld_rlx2(const void* p) { uint2 v; asm volatile("ld.relaxed.gpu.global.v2.b32 {%0,%1}, [%2];" : "=r"(v.x), "=r"(v.y) : "l"(p) : "memory"); return v; }
__device__ __forceinline__ uint4 ld_rlx4(const void* p) { uint4 v; asm volatile("ld.relaxed.gpu.global.v4.b32 {%0,%1,%2,%3}, [%4];" : "=r"(v.x), "=r"(v.y), "=r"(v.z), "=r"(v.w) : "l"(p) : "memory"); return v; }
__device__ __forceinline__ uint32_t ld_nc(const void* p) { uint32_t v; asm volatile("ld.global.nc.L1::no_allocate.b32 %0, [%1];" : "=r"(v) : "l"(p) : "memory"); return v; }
__device__ __forceinline__ uint4 ld_nc4(const void* p) { uint4 v; asm volatile("ld.global.nc.v4.b32 {%0,%1,%2,%3}, [%4];" : "=r"(v.x), "=r"(v.y), "=r"(v.z), "=r"(v.w) : "l"(p) : "memory"); return v; }
__device__ __forceinline__ uint32_t lds(uint32_t a) { uint32_t v; asm volatile("ld.shared.b32 %0, [%1];" : "=r"(v) : "r"(a) : "memory"); return v; }
__device__ __forceinline__ uint2 lds2(uint32_t a) { uint2 v; asm volatile("ld.shared.v2.b32 {%0,%1}, [%2];" : "=r"(v.x), "=r"(v.y) : "r"(a) : "memory"); return v; }
__device__ __forceinline__ uint4 lds4(uint32_t a) { uint4 v; asm volatile("ld.shared.v4.b32 {%0,%1,%2,%3}, [%4];" : "=r"(v.x), "=r"(v.y), "=r"(v.z), "=r"(v.w) : "r"(a) : "memory"); return v; }
__device__ __forceinline__ float lds_bf(uint32_t a) { uint32_t v; asm volatile("ld.shared.u16 %0, [%1];" : "=r"(v) : "r"(a) : "memory"); return __uint_as_float(v << 16); }
__device__ __forceinline__ void sts(uint32_t a, uint32_t v) { asm volatile("st.shared.b32 [%0], %1;" ::"r"(a), "r"(v) : "memory"); }
__device__ __forceinline__ void sts2(uint32_t a, uint32_t v0, uint32_t v1) { asm volatile("st.shared.v2.b32 [%0], {%1,%2};" ::"r"(a), "r"(v0), "r"(v1) : "memory"); }
__device__ __forceinline__ void sts4(uint32_t a, uint32_t v0, uint32_t v1, uint32_t v2, uint32_t v3) { asm volatile("st.shared.v4.b32 [%0], {%1,%2,%3,%4};" ::"r"(a), "r"(v0), "r"(v1), "r"(v2), "r"(v3) : "memory"); }
__device__ __forceinline__ void bar_sync(int id, int n) { asm volatile("bar.sync %0, %1;" ::"r"(id), "r"(n) : "memory"); }
__device__ __forceinline__ void bar_arrive(int id, int n) { asm volatile("bar.arrive %0, %1;" ::"r"(id), "r"(n) : "memory"); }
__device__ __forceinline__ void red_add(unsigned* p, unsigned v) { asm volatile("red.relaxed.gpu.global.add.u32 [%0], %1;" ::"l"(p), "r"(v) : "memory"); }
__device__ __forceinline__ bool any(bool p) { return __any_sync(0xffffffffu, p); }
__device__ __forceinline__ void pause(unsigned clks) {
  asm volatile("{\n.reg .pred p;\n.reg .u32 a, b;\nmov.u32 a, %%clock;\nW:\nmov.u32 b, %%clock;\nsub.u32 b, b, a;\nsetp.lt.s32 p, b, %0;\n@p bra.uni W;\n}" ::"r"(clks) : "memory");
}
__device__ __forceinline__ void red_bf16x8(uint32_t* p, uint32_t a, uint32_t b, uint32_t c, uint32_t d) {
  asm volatile("red.relaxed.gpu.global.add.noftz.v4.bf16x2 [%0], {%1,%2,%3,%4};" ::"l"(p), "r"(a), "r"(b), "r"(c), "r"(d) : "memory");
}
__device__ __forceinline__ void red_bf16x4(uint32_t* p, uint32_t a, uint32_t b) {
  asm volatile("red.relaxed.gpu.global.add.noftz.v2.bf16x2 [%0], {%1,%2};" ::"l"(p), "r"(a), "r"(b) : "memory");
}
constexpr int SPIN_MAX = 1 << 20;
__device__ __forceinline__ uint32_t ld_acq(const void* p) { uint32_t v; asm volatile("ld.acquire.gpu.global.b32 %0, [%1];" : "=r"(v) : "l"(p) : "memory"); return v; }
template <bool ACQ = false> __device__ __forceinline__ void wait_cnt(const unsigned* p, unsigned target) {
  int it = 0;
  while (any((int)((ACQ ? ld_acq(p) : ld_rlx(p)) - target) < 0) && ++it < SPIN_MAX) {}
}
__device__ __forceinline__ uint32_t pack_bf16(float lo, float hi) { uint32_t r; asm("cvt.rn.bf16x2.f32 %0, %1, %2;" : "=r"(r) : "f"(hi), "f"(lo)); return r; }
__device__ __forceinline__ float bf_lo(uint32_t v) { return __uint_as_float(v << 16); }
__device__ __forceinline__ float bf_hi(uint32_t v) { return __uint_as_float(v & 0xffff0000u); }
__device__ __forceinline__ uint32_t hadd2(uint32_t a, uint32_t b) { uint32_t r; asm("add.rn.bf16x2 %0, %1, %2;" : "=r"(r) : "r"(a), "r"(b)); return r; }
__device__ __forceinline__ uint32_t hmul2(uint32_t a, uint32_t b) { uint32_t r; asm("mul.rn.bf16x2 %0, %1, %2;" : "=r"(r) : "r"(a), "r"(b)); return r; }
__device__ __forceinline__ uint32_t hfma2(uint32_t a, uint32_t b, uint32_t c) { uint32_t r; asm("fma.rn.bf16x2 %0, %1, %2, %3;" : "=r"(r) : "r"(a), "r"(b), "r"(c)); return r; }
__device__ __forceinline__ float rbf(float x) { uint32_t r; asm("cvt.rn.bf16x2.f32 %0, %1, %2;" : "=r"(r) : "f"(x), "f"(0.0f)); return __uint_as_float(r); }
__device__ __forceinline__ void stmatrix4(uint32_t a, uint32_t r0, uint32_t r1, uint32_t r2, uint32_t r3) {
  asm volatile("stmatrix.sync.aligned.m8n8.x4.shared.b16 [%0], {%1,%2,%3,%4};" ::"r"(a), "r"(r0), "r"(r1), "r"(r2), "r"(r3) : "memory");
}
__device__ __forceinline__ void stmatrix2(uint32_t a, uint32_t r0, uint32_t r1) {
  asm volatile("stmatrix.sync.aligned.m8n8.x2.shared.b16 [%0], {%1,%2};" ::"r"(a), "r"(r0), "r"(r1) : "memory");
}
__device__ __forceinline__ void stmatrix4t(uint32_t a, uint32_t r0, uint32_t r1, uint32_t r2, uint32_t r3) {
  asm volatile("stmatrix.sync.aligned.m8n8.x4.trans.shared.b16 [%0], {%1,%2,%3,%4};" ::"r"(a), "r"(r0), "r"(r1), "r"(r2), "r"(r3) : "memory");
}
__device__ __forceinline__ uint32_t movm(uint32_t a) { uint32_t r; asm("movmatrix.sync.aligned.m8n8.trans.b16 %0, %1;" : "=r"(r) : "r"(a)); return r; }
template <bool ACC> __device__ __forceinline__ void mma16(float* d, uint32_t a0, uint32_t a1, uint32_t a2, uint32_t a3, uint32_t b0, uint32_t b1) {
  if (ACC) asm("mma.sync.aligned.m16n8k16.row.col.f32.bf16.bf16.f32 {%0,%1,%2,%3}, {%4,%5,%6,%7}, {%8,%9}, {%0,%1,%2,%3};"
               : "+f"(d[0]), "+f"(d[1]), "+f"(d[2]), "+f"(d[3]) : "r"(a0), "r"(a1), "r"(a2), "r"(a3), "r"(b0), "r"(b1));
  else asm("mma.sync.aligned.m16n8k16.row.col.f32.bf16.bf16.f32 {%0,%1,%2,%3}, {%4,%5,%6,%7}, {%8,%9}, {%10,%10,%10,%10};"
           : "=f"(d[0]), "=f"(d[1]), "=f"(d[2]), "=f"(d[3]) : "r"(a0), "r"(a1), "r"(a2), "r"(a3), "r"(b0), "r"(b1), "f"(0.f));
}
__device__ __forceinline__ uint32_t pin(uint32_t v) { uint32_t r; asm volatile("shfl.sync.bfly.b32 %0, %1, 0, 31, 0xffffffff;" : "=r"(r) : "r"(v)); return r; }
template <class T> __device__ __forceinline__ T* pin(T* p) {
  const uint64_t a = reinterpret_cast<uint64_t>(p);
  return reinterpret_cast<T*>((uint64_t)pin((uint32_t)a) | ((uint64_t)pin((uint32_t)(a >> 32)) << 32));
}
__device__ __forceinline__ uint32_t upin(uint32_t v) { return __shfl_sync(0xffffffffu, v, 0); }
template <class T> __device__ __forceinline__ T* upin(T* p) {
  const uint64_t a = reinterpret_cast<uint64_t>(p);
  return reinterpret_cast<T*>((uint64_t)upin((uint32_t)a) | ((uint64_t)upin((uint32_t)(a >> 32)) << 32));
}
__device__ __forceinline__ bool elect() {
  uint32_t p;
  asm volatile("{\n.reg .pred P;\nelect.sync _|P, 0xffffffff;\nselp.u32 %0, 1, 0, P;\n}" : "=r"(p));
  return p;
}
__device__ __forceinline__ uint32_t set_tag(uint32_t w, uint32_t tag) { uint32_t r; asm("lop3.b32 %0, %1, 0xfffffffe, %2, 0xea;" : "=r"(r) : "r"(w), "r"(tag)); return r; }
__device__ __forceinline__ uint32_t bitsel(uint32_t w, uint32_t m, uint32_t o) { uint32_t r; asm("lop3.b32 %0, %1, %2, %3, 0xe2;" : "=r"(r) : "r"(w), "r"(m), "r"(o)); return r; }
__device__ __forceinline__ uint32_t or3(uint32_t a, uint32_t b, uint32_t c) { uint32_t r; asm("lop3.b32 %0, %1, %2, %3, 0xfe;" : "=r"(r) : "r"(a), "r"(b), "r"(c)); return r; }
__device__ __forceinline__ uint32_t diff2(uint32_t a, uint32_t b, uint32_t tag) { uint32_t r; asm("lop3.b32 %0, %1, %2, %3, 0x7e;" : "=r"(r) : "r"(a), "r"(b), "r"(tag)); return r; }
__device__ __forceinline__ float2 cmul(float2 a, float2 b) { return make_float2(a.x * b.x - a.y * b.y, a.x * b.y + a.y * b.x); }

template<int TB> __device__ __forceinline__ void wgmma_ss_160_0(float (&d)[96], uint32_t al, uint32_t ah, uint32_t bl, uint32_t bh) {
  asm volatile("{\n.reg .b64 da, db;\nmov.b64 da, {%80, %81};\nmov.b64 db, {%82, %83};\n"
    "wgmma.mma_async.sync.aligned.m64n160k16.f32.bf16.bf16 {%0,%1,%2,%3,%4,%5,%6,%7,%8,%9,%10,%11,%12,%13,%14,%15,%16,%17,%18,%19,%20,%21,%22,%23,%24,%25,%26,%27,%28,%29,%30,%31,%32,%33,%34,%35,%36,%37,%38,%39,%40,%41,%42,%43,%44,%45,%46,%47,%48,%49,%50,%51,%52,%53,%54,%55,%56,%57,%58,%59,%60,%61,%62,%63,%64,%65,%66,%67,%68,%69,%70,%71,%72,%73,%74,%75,%76,%77,%78,%79}, da, db, 1, 1, 1, 1, %84;\n}\n"
    : "+f"(d[0]),"+f"(d[1]),"+f"(d[2]),"+f"(d[3]),"+f"(d[4]),"+f"(d[5]),"+f"(d[6]),"+f"(d[7]),"+f"(d[8]),"+f"(d[9]),"+f"(d[10]),"+f"(d[11]),"+f"(d[12]),"+f"(d[13]),"+f"(d[14]),"+f"(d[15]),"+f"(d[16]),"+f"(d[17]),"+f"(d[18]),"+f"(d[19]),"+f"(d[20]),"+f"(d[21]),"+f"(d[22]),"+f"(d[23]),"+f"(d[24]),"+f"(d[25]),"+f"(d[26]),"+f"(d[27]),"+f"(d[28]),"+f"(d[29]),"+f"(d[30]),"+f"(d[31]),"+f"(d[32]),"+f"(d[33]),"+f"(d[34]),"+f"(d[35]),"+f"(d[36]),"+f"(d[37]),"+f"(d[38]),"+f"(d[39]),"+f"(d[40]),"+f"(d[41]),"+f"(d[42]),"+f"(d[43]),"+f"(d[44]),"+f"(d[45]),"+f"(d[46]),"+f"(d[47]),"+f"(d[48]),"+f"(d[49]),"+f"(d[50]),"+f"(d[51]),"+f"(d[52]),"+f"(d[53]),"+f"(d[54]),"+f"(d[55]),"+f"(d[56]),"+f"(d[57]),"+f"(d[58]),"+f"(d[59]),"+f"(d[60]),"+f"(d[61]),"+f"(d[62]),"+f"(d[63]),"+f"(d[64]),"+f"(d[65]),"+f"(d[66]),"+f"(d[67]),"+f"(d[68]),"+f"(d[69]),"+f"(d[70]),"+f"(d[71]),"+f"(d[72]),"+f"(d[73]),"+f"(d[74]),"+f"(d[75]),"+f"(d[76]),"+f"(d[77]),"+f"(d[78]),"+f"(d[79])
    : "r"(al), "r"(ah), "r"(bl), "r"(bh), "n"(TB));
}
template<int TB> __device__ __forceinline__ void wgmma_ss_144_0(float (&d)[96], uint32_t al, uint32_t ah, uint32_t bl, uint32_t bh) {
  asm volatile("{\n.reg .b64 da, db;\nmov.b64 da, {%72, %73};\nmov.b64 db, {%74, %75};\n"
    "wgmma.mma_async.sync.aligned.m64n144k16.f32.bf16.bf16 {%0,%1,%2,%3,%4,%5,%6,%7,%8,%9,%10,%11,%12,%13,%14,%15,%16,%17,%18,%19,%20,%21,%22,%23,%24,%25,%26,%27,%28,%29,%30,%31,%32,%33,%34,%35,%36,%37,%38,%39,%40,%41,%42,%43,%44,%45,%46,%47,%48,%49,%50,%51,%52,%53,%54,%55,%56,%57,%58,%59,%60,%61,%62,%63,%64,%65,%66,%67,%68,%69,%70,%71}, da, db, 1, 1, 1, 1, %76;\n}\n"
    : "+f"(d[0]),"+f"(d[1]),"+f"(d[2]),"+f"(d[3]),"+f"(d[4]),"+f"(d[5]),"+f"(d[6]),"+f"(d[7]),"+f"(d[8]),"+f"(d[9]),"+f"(d[10]),"+f"(d[11]),"+f"(d[12]),"+f"(d[13]),"+f"(d[14]),"+f"(d[15]),"+f"(d[16]),"+f"(d[17]),"+f"(d[18]),"+f"(d[19]),"+f"(d[20]),"+f"(d[21]),"+f"(d[22]),"+f"(d[23]),"+f"(d[24]),"+f"(d[25]),"+f"(d[26]),"+f"(d[27]),"+f"(d[28]),"+f"(d[29]),"+f"(d[30]),"+f"(d[31]),"+f"(d[32]),"+f"(d[33]),"+f"(d[34]),"+f"(d[35]),"+f"(d[36]),"+f"(d[37]),"+f"(d[38]),"+f"(d[39]),"+f"(d[40]),"+f"(d[41]),"+f"(d[42]),"+f"(d[43]),"+f"(d[44]),"+f"(d[45]),"+f"(d[46]),"+f"(d[47]),"+f"(d[48]),"+f"(d[49]),"+f"(d[50]),"+f"(d[51]),"+f"(d[52]),"+f"(d[53]),"+f"(d[54]),"+f"(d[55]),"+f"(d[56]),"+f"(d[57]),"+f"(d[58]),"+f"(d[59]),"+f"(d[60]),"+f"(d[61]),"+f"(d[62]),"+f"(d[63]),"+f"(d[64]),"+f"(d[65]),"+f"(d[66]),"+f"(d[67]),"+f"(d[68]),"+f"(d[69]),"+f"(d[70]),"+f"(d[71])
    : "r"(al), "r"(ah), "r"(bl), "r"(bh), "n"(TB));
}
template<int TB> __device__ __forceinline__ void wgmma_ss_96_0(float (&d)[96], uint32_t al, uint32_t ah, uint32_t bl, uint32_t bh) {
  asm volatile("{\n.reg .b64 da, db;\nmov.b64 da, {%48, %49};\nmov.b64 db, {%50, %51};\n"
    "wgmma.mma_async.sync.aligned.m64n96k16.f32.bf16.bf16 {%0,%1,%2,%3,%4,%5,%6,%7,%8,%9,%10,%11,%12,%13,%14,%15,%16,%17,%18,%19,%20,%21,%22,%23,%24,%25,%26,%27,%28,%29,%30,%31,%32,%33,%34,%35,%36,%37,%38,%39,%40,%41,%42,%43,%44,%45,%46,%47}, da, db, 1, 1, 1, 1, %52;\n}\n"
    : "+f"(d[0]),"+f"(d[1]),"+f"(d[2]),"+f"(d[3]),"+f"(d[4]),"+f"(d[5]),"+f"(d[6]),"+f"(d[7]),"+f"(d[8]),"+f"(d[9]),"+f"(d[10]),"+f"(d[11]),"+f"(d[12]),"+f"(d[13]),"+f"(d[14]),"+f"(d[15]),"+f"(d[16]),"+f"(d[17]),"+f"(d[18]),"+f"(d[19]),"+f"(d[20]),"+f"(d[21]),"+f"(d[22]),"+f"(d[23]),"+f"(d[24]),"+f"(d[25]),"+f"(d[26]),"+f"(d[27]),"+f"(d[28]),"+f"(d[29]),"+f"(d[30]),"+f"(d[31]),"+f"(d[32]),"+f"(d[33]),"+f"(d[34]),"+f"(d[35]),"+f"(d[36]),"+f"(d[37]),"+f"(d[38]),"+f"(d[39]),"+f"(d[40]),"+f"(d[41]),"+f"(d[42]),"+f"(d[43]),"+f"(d[44]),"+f"(d[45]),"+f"(d[46]),"+f"(d[47])
    : "r"(al), "r"(ah), "r"(bl), "r"(bh), "n"(TB));
}
template<int TB> __device__ __forceinline__ void wgmma_ss_96_48(float (&d)[96], uint32_t al, uint32_t ah, uint32_t bl, uint32_t bh) {
  asm volatile("{\n.reg .b64 da, db;\nmov.b64 da, {%48, %49};\nmov.b64 db, {%50, %51};\n"
    "wgmma.mma_async.sync.aligned.m64n96k16.f32.bf16.bf16 {%0,%1,%2,%3,%4,%5,%6,%7,%8,%9,%10,%11,%12,%13,%14,%15,%16,%17,%18,%19,%20,%21,%22,%23,%24,%25,%26,%27,%28,%29,%30,%31,%32,%33,%34,%35,%36,%37,%38,%39,%40,%41,%42,%43,%44,%45,%46,%47}, da, db, 1, 1, 1, 1, %52;\n}\n"
    : "+f"(d[48]),"+f"(d[49]),"+f"(d[50]),"+f"(d[51]),"+f"(d[52]),"+f"(d[53]),"+f"(d[54]),"+f"(d[55]),"+f"(d[56]),"+f"(d[57]),"+f"(d[58]),"+f"(d[59]),"+f"(d[60]),"+f"(d[61]),"+f"(d[62]),"+f"(d[63]),"+f"(d[64]),"+f"(d[65]),"+f"(d[66]),"+f"(d[67]),"+f"(d[68]),"+f"(d[69]),"+f"(d[70]),"+f"(d[71]),"+f"(d[72]),"+f"(d[73]),"+f"(d[74]),"+f"(d[75]),"+f"(d[76]),"+f"(d[77]),"+f"(d[78]),"+f"(d[79]),"+f"(d[80]),"+f"(d[81]),"+f"(d[82]),"+f"(d[83]),"+f"(d[84]),"+f"(d[85]),"+f"(d[86]),"+f"(d[87]),"+f"(d[88]),"+f"(d[89]),"+f"(d[90]),"+f"(d[91]),"+f"(d[92]),"+f"(d[93]),"+f"(d[94]),"+f"(d[95])
    : "r"(al), "r"(ah), "r"(bl), "r"(bh), "n"(TB));
}
__device__ __forceinline__ void wgmma_rs_72(float (&d)[36], uint32_t a0, uint32_t a1, uint32_t a2, uint32_t a3, uint32_t bl, uint32_t bh, int sd) {
  asm volatile("{\n.reg .pred p;\n.reg .b64 db;\nsetp.ne.b32 p, %42, 0;\nmov.b64 db, {%40, %41};\n"
    "wgmma.mma_async.sync.aligned.m64n72k16.f32.bf16.bf16 {%0,%1,%2,%3,%4,%5,%6,%7,%8,%9,%10,%11,%12,%13,%14,%15,%16,%17,%18,%19,%20,%21,%22,%23,%24,%25,%26,%27,%28,%29,%30,%31,%32,%33,%34,%35}, {%36,%37,%38,%39}, db, p, 1, 1, 1;\n}\n"
    : "+f"(d[0]),"+f"(d[1]),"+f"(d[2]),"+f"(d[3]),"+f"(d[4]),"+f"(d[5]),"+f"(d[6]),"+f"(d[7]),"+f"(d[8]),"+f"(d[9]),"+f"(d[10]),"+f"(d[11]),"+f"(d[12]),"+f"(d[13]),"+f"(d[14]),"+f"(d[15]),"+f"(d[16]),"+f"(d[17]),"+f"(d[18]),"+f"(d[19]),"+f"(d[20]),"+f"(d[21]),"+f"(d[22]),"+f"(d[23]),"+f"(d[24]),"+f"(d[25]),"+f"(d[26]),"+f"(d[27]),"+f"(d[28]),"+f"(d[29]),"+f"(d[30]),"+f"(d[31]),"+f"(d[32]),"+f"(d[33]),"+f"(d[34]),"+f"(d[35])
    : "r"(a0), "r"(a1), "r"(a2), "r"(a3), "r"(bl), "r"(bh), "r"(sd));
}
__device__ __forceinline__ void wgmma_rs_48(float (&d)[24], uint32_t a0, uint32_t a1, uint32_t a2, uint32_t a3, uint32_t bl, uint32_t bh, int sd) {
  asm volatile("{\n.reg .pred p;\n.reg .b64 db;\nsetp.ne.b32 p, %30, 0;\nmov.b64 db, {%28, %29};\n"
    "wgmma.mma_async.sync.aligned.m64n48k16.f32.bf16.bf16 {%0,%1,%2,%3,%4,%5,%6,%7,%8,%9,%10,%11,%12,%13,%14,%15,%16,%17,%18,%19,%20,%21,%22,%23}, {%24,%25,%26,%27}, db, p, 1, 1, 1;\n}\n"
    : "+f"(d[0]),"+f"(d[1]),"+f"(d[2]),"+f"(d[3]),"+f"(d[4]),"+f"(d[5]),"+f"(d[6]),"+f"(d[7]),"+f"(d[8]),"+f"(d[9]),"+f"(d[10]),"+f"(d[11]),"+f"(d[12]),"+f"(d[13]),"+f"(d[14]),"+f"(d[15]),"+f"(d[16]),"+f"(d[17]),"+f"(d[18]),"+f"(d[19]),"+f"(d[20]),"+f"(d[21]),"+f"(d[22]),"+f"(d[23])
    : "r"(a0), "r"(a1), "r"(a2), "r"(a3), "r"(bl), "r"(bh), "r"(sd));
}
template<int N,int OFF,int TB> __device__ __forceinline__ void wgmma_ss(float (&d)[96], uint32_t al, uint32_t ah, uint32_t bl, uint32_t bh) {
  if constexpr (N==160 && OFF==0) wgmma_ss_160_0<TB>(d, al, ah, bl, bh);
  else if constexpr (N==144 && OFF==0) wgmma_ss_144_0<TB>(d, al, ah, bl, bh);
  else if constexpr (N==96 && OFF==0) wgmma_ss_96_0<TB>(d, al, ah, bl, bh);
  else if constexpr (N==96 && OFF==48) wgmma_ss_96_48<TB>(d, al, ah, bl, bh);
}

__device__ __forceinline__ void dft3(float2& a, float2& b, float2& c) {
  const float s = 0.86602540378443864676f;
  float2 t = make_float2(b.x + c.x, b.y + c.y), d = make_float2(b.x - c.x, b.y - c.y);
  float2 m = make_float2(fmaf(-0.5f, t.x, a.x), fmaf(-0.5f, t.y, a.y));
  a = make_float2(a.x + t.x, a.y + t.y);
  b = make_float2(fmaf(s, d.y, m.x), fmaf(-s, d.x, m.y));
  c = make_float2(fmaf(-s, d.y, m.x), fmaf(s, d.x, m.y));
}
__device__ __forceinline__ void dft9(float2 (&x)[9]) {
  const float2 w1 = make_float2(0.76604444311897803520f, -0.64278760968653932632f);
  const float2 w2 = make_float2(0.17364817766693034885f, -0.98480775301220805937f);
  const float2 w4 = make_float2(-0.93969262078590838405f, -0.34202014332566873304f);
  dft3(x[0], x[3], x[6]); dft3(x[1], x[4], x[7]); dft3(x[2], x[5], x[8]);
  x[4] = cmul(x[4], w1); x[7] = cmul(x[7], w2); x[5] = cmul(x[5], w2); x[8] = cmul(x[8], w4);
  dft3(x[0], x[1], x[2]); dft3(x[3], x[4], x[5]); dft3(x[6], x[7], x[8]);
  float2 t;
  t = x[1]; x[1] = x[3]; x[3] = t;
  t = x[2]; x[2] = x[6]; x[6] = t;
  t = x[5]; x[5] = x[7]; x[7] = t;
}

__device__ __forceinline__ uint32_t* mod_ptr(Scratch* sc, int u, int t128) {
  const int i = t128 & 15;
  return u < 72 ? sc->moda + (t128 >> 4) * (2 * D_) + 16 * u + 2 * (i & 7) + (i >> 3) : sc->mod + 16 * (u - 72) + i;
}
__device__ __forceinline__ void mod_unit(Scratch* sc, int u, int t128, uint32_t sw_, uint32_t bar, int ph, uint32_t rb, uint32_t tag) {
  const int w = t128 >> 5, l = t128 & 31;
  uint32_t b[18];
#pragma unroll
  for (int i = 0; i < 18; i++) b[i] = lds(red + 512 + (72 * w + 4 * i + (l & 3)) * 4);
  const uint32_t sa = pin(sw_ + (144 * w + (l & 7) + 8 * (l >> 4)) * 32 + (((l >> 3) ^ (l >> 2)) & 1) * 16);
  const uint32_t sr = pin(rb + (l >> 2) * 16 + w * 4);
  uint32_t* const dst = pin(mod_ptr(sc, u, t128));
  const int kind = u / 36;
  const float mul = __uint_as_float(pin(__float_as_uint(kind == 0 ? 16.0f : 1.0f))), add = __uint_as_float(pin(__float_as_uint(kind == 1 || kind == 4 ? 1.0f : 0.0f)));
  mbar_wait(bar, ph);
  if (t128 == 0 && u < 72) TS(10);
  float d[3][4];
#pragma unroll
  for (int i = 0; i < 9; i++) {
    uint32_t a0, a1, a2, a3;
    asm volatile("ldmatrix.sync.aligned.m8n8.x4.trans.shared.b16 {%0,%1,%2,%3}, [%4];" : "=r"(a0), "=r"(a1), "=r"(a2), "=r"(a3) : "r"(sa + i * 512) : "memory");
    if (i < 3) mma16<false>(d[i], a0, a1, a2, a3, b[2 * i], b[2 * i + 1]);
    else mma16<true>(d[i % 3], a0, a1, a2, a3, b[2 * i], b[2 * i + 1]);
  }
  if ((l & 3) == 0) { sts(sr, __float_as_uint(d[0][0] + d[1][0] + d[2][0])); sts(sr + 128, __float_as_uint(d[0][2] + d[1][2] + d[2][2])); }
  bar_sync(4, 128);
  const uint4 v = lds4(rb + (l & 15) * 16);
  const float m = rbf(fmaf(rbf((__uint_as_float(v.x) + __uint_as_float(v.y)) + (__uint_as_float(v.z) + __uint_as_float(v.w))), mul, add));
  if (u < 72 || t128 < 16) *dst = __float_as_uint(m) | tag;
}

__device__ __forceinline__ float rsq(float x) { float r; asm("rsqrt.approx.ftz.f32 %0, %1;" : "=f"(r) : "f"(x)); return r; }
__device__ __forceinline__ void ln_stats2(const float (&a)[18], const float (&b)[18], float sc, float& oa, float& ra, float& ob, float& rb) {
  float v[4] = {0.f, 0.f, 0.f, 0.f}, w[4] = {0.f, 0.f, 0.f, 0.f};
#pragma unroll
  for (int i = 0; i < 18; i += 2) {
    v[0] += a[i]; v[1] = fmaf(a[i], a[i], v[1]); v[2] += b[i]; v[3] = fmaf(b[i], b[i], v[3]);
    w[0] += a[i + 1]; w[1] = fmaf(a[i + 1], a[i + 1], w[1]); w[2] += b[i + 1]; w[3] = fmaf(b[i + 1], b[i + 1], w[3]);
  }
#pragma unroll
  for (int e = 0; e < 4; e++) v[e] += w[e];
#pragma unroll
  for (int o = 16; o; o >>= 1) {
#pragma unroll
    for (int e = 0; e < 4; e++) v[e] += __shfl_xor_sync(0xffffffffu, v[e], o);
  }
  const float ma = v[0] * (1.0f / D_), mb = v[2] * (1.0f / D_);
  ra = sc * rsq(fmaxf(fmaf(-ma, ma, v[1] * (1.0f / D_)), 0.f) + 1e-5f);
  rb = sc * rsq(fmaxf(fmaf(-mb, mb, v[3] * (1.0f / D_)), 0.f) + 1e-5f);
  oa = -ma * ra; ob = -mb * rb;
}

__device__ __forceinline__ float tmat(int c, int q, int j) {
  const int ph = q == 1 ? 1024 * j : (q >> 1) * (c + 128 * j) + 512 * (q & 1);
  return __cosf((float)(((ph + 1024) & 2047) - 1024) * (6.283185307179586f / 2048.0f));
}
__device__ __forceinline__ uint32_t line_off(int k1, int kap, int pi, int f) {
  int kd = 64 * k1 + 9 * kap;
  if (kap == 0 && k1 > 4) kd -= 288;
  if (kd >= D_) kd -= D_;
  return pi * 2400 + ((min(kd, D_ - kd) ^ f) << 3);
}

constexpr int JSK = 5;
struct Ring { uint32_t st, ph; };
template <bool G2, class T> __device__ __forceinline__ void ring_next(T& st, T& ph) {
  if (++st == NST) st = 0;
  ph ^= ((G2 ? 0xDu : 0x1u) >> st) & 1;
}
__device__ __forceinline__ void arrive_if(uint32_t a, uint32_t p) {
  asm volatile("{\n.reg .pred p;\nsetp.ne.u32 p, %1, 0;\n@p mbarrier.arrive.shared::cta.b64 _, [%0];\n}" ::"r"(a), "r"(p) : "memory");
}
template <int NA> __device__ __forceinline__ void reg_fence_n(float (&d)[96]) {
#pragma unroll
  for (int i = 0; i < NA; i++) asm volatile("" : "+f"(d[i])::"memory");
}
template <int MODE>
__device__ __forceinline__ void gemm_main(float (&acc)[96], uint32_t da0, uint32_t da1, uint32_t db0, int wg, Ring& rg,
                                          bool rows, uint32_t* x1p, const uint32_t (&xr)[18]) {
  static_assert(JSK == NST - 1, "the held slot is the first one that is not refilled by GEMM1");
  constexpr int NKB = MODE == 3 ? 36 : 32, J = MODE == 3 ? J2 : JSK;
  constexpr uint32_t HA = 0x40000040u, HB = MODE == 3 ? 0x40000040u : 0x80000020u;
  constexpr uint32_t KA = 2048 >> 4, KB = MODE == 3 ? (32 >> 4) : (1024 >> 4);
  constexpr int NA = MODE == 3 ? 72 : MODE == 1 ? 96 : 80;
  const uint32_t t = threadIdx.x & 127;
  const uint32_t eb = full0 + 8 * NST;
  uint32_t pb = 0, rel = t == 0, prel = 0, ok = 0;
  int n = MODE == 3 ? NKB - J : X1K + 2 * wg;
#pragma unroll 1
  for (int pass = MODE == 3 ? 0 : -1;; pass++) {
#pragma unroll 1
    do {
      const uint32_t so = rg.st * ((MODE == 3 ? STAGE2 : STAGE) >> 4), cb = eb + 8 * rg.st;
      if (__builtin_expect(!ok, 0)) mbar_wait(full0 + 8 * rg.st, rg.ph);
      reg_fence_n<NA>(acc);
      if (MODE == 1 && wg) {
        wg_fence();
#pragma unroll
        for (int k = 0; k < 4; k++) wgmma_ss<96, 48, 1>(acc, da1 + so + k * KA, HA, db0 + so + k * KB, HB);
        wg_commit();
      }
      wg_fence();
#pragma unroll
      for (int k = 0; k < 4; k++) {
        if (k == 3) { ring_next<MODE == 3>(rg.st, rg.ph); ok = PEEK ? mbar_test(full0 + 8 * rg.st, rg.ph) : 0; }
        if (MODE == 0) wgmma_ss<160, 0, 1>(acc, da0 + so + k * KA, HA, db0 + so + k * KB, HB);
        else if (MODE == 3) wgmma_ss<144, 0, 0>(acc, da0 + so + k * KA, HA, db0 + so + k * KB, HB);
        else wgmma_ss<96, 0, 1>(acc, da0 + so + k * KA, HA, db0 + so + k * KB, HB);
      }
      wg_commit();
      wg_wait<1>();
      reg_fence_n<NA>(acc);
      arrive_if(pb, prel);
      pb = cb; prel = rel;
    } while (--n);
    if (pass == 2 - wg) break;
    if (MODE != 3 && pass < 0) {
      if (rows) {
#pragma unroll
        for (int i = 0; i < 9; i++) { x1p[32 * i] = xr[i]; x1p[128 * 288 + 32 * i] = xr[9 + i]; }
      }
      n = NKB - JSK - X1K - 2 * wg;
      continue;
    }
    n = 1;
    if (pass == 0) {
      if (MODE != 3) prel = rel & wg;
      else { rel = 0; if (J < NST) prel = 0; }
      n = J - 1 + wg;
      if (!wg) continue;
      wg_wait<0>();
      arrive_if(pb, prel);
      prel = 0;
    }
    bar_sync(1, 256);
  }
  wg_wait<0>();
  reg_fence_n<NA>(acc);
  if (MODE != 3) arrive_if(pb, MODE == 1 ? prel & ~wg : prel);
}

constexpr float GK1 = 2.0f * 0.7978845608028654f, GK3 = 8.0f * 0.044715f * 0.7978845608028654f;

__device__ __forceinline__ int kb2_order(int i) { const int wv = i / 6; return 6 * (i - 6 * wv) + ((0x431250 >> (4 * wv)) & 7); }

__device__ __forceinline__ int kb2_pos(int kb) { const int hf = kb >= 36, k = kb - 36 * hf, gr = k / 6; return 64 * hf + gr + 6 * ((0x154230 >> (4 * (k - 6 * gr))) & 7); }

__device__ __forceinline__ void wait_flags(const unsigned* p, int idx, unsigned target, uint32_t& ready) {
  int it = 0;
  while (!((ready >> idx) & 1) && it++ < SPIN_MAX) ready = __ballot_sync(0xffffffffu, (int)(ld_rlx(p) - target) >= 0);
}

enum { B_FULL = 0, B_EMPTY = 6, B_S4 = 12, B_S5, B_LAND, B_FLT = B_LAND + 6, B_Z1, B_Z2, B_GO, B_X, B_WM, B_NUM, B_W0 = B_NUM };

__global__ void __launch_bounds__(NTHR, 1)
fused_kernel(const Params p, const __grid_constant__ Maps maps) {
  extern __shared__ __align__(1024) uint8_t smem_raw[];
  const int bx = blockIdx.x, cta = bx < 112 || bx >= 130 ? bx : bx < 114 ? bx + 16 : bx - 2;
  const int tid = threadIdx.x, t128 = tid & 127;
  const int wp = __shfl_sync(0xffffffffu, tid >> 5, 0), wg = wp >> 2;
  const int l = tid & 31, g = l >> 2, t = l & 3;
  Scratch* const sc = p.s;
  const bool rows = cta < 128;
  const int mu = rows ? cta + 4 : cta - 128;
  const int R = mu - 12;

  uint32_t xr[18];
  uint32_t cv[3];
  const unsigned ep0 = ld_rlx(&sc->cnt[C_EP]);
  if (tid == 0) TS(0);
  if (wg == 2) {
#pragma unroll
    for (int i = 0; i < 3; i++) cv[i] = ld_nc(reinterpret_cast<const uint32_t*>(p.c) + min(t128 + 128 * i, 287));
    if (wp == 9 && l < 9 && rows) {
      const int h = 9 * cta + l;
      prefetch_l2(reinterpret_cast<const uint8_t*>(p.wmod) + (size_t)(h >> 1) * (12 * D_) + (h & 1) * (2 * D_), 2 * D_);
    }
    if (tid == 256 && mu < 72) {
      mbar_init(full0 + 8 * B_W0, 1);
      fence_async_smem();
      mbar_expect(full0 + 8 * B_W0, 18432);
#pragma unroll 1
      for (int i = 0; i < 3; i++) tma2d(sbase + O_P2 + i * 6144, &maps.wm, 16 * mu, 192 * i, full0 + 8 * B_W0);
    }
    __syncwarp();
#pragma unroll 1
    for (int u = mu < 72 ? mu : 72 + mu; u < 216; u += u < 72 ? 72 : NCTA) if (u < 72 || t128 < 16) *mod_ptr(sc, u, t128) = 0;
    if (wp == 11 && smem_u32(smem_raw) != sbase) __trap();
    if (wp >= 10 && elect()) {
#pragma unroll 1
      for (int i = wp - 10; i < B_NUM; i += 2) mbar_init(full0 + 8 * i, i == B_FLT ? 4 : i == B_WM ? 3 : i < B_LAND && i != B_S4 ? 2 : 1);
      fence_async_smem();
    }
    __syncwarp();
  }
  CK(0);
  auto load_x = [&]() {
    const uint32_t* xs = reinterpret_cast<const uint32_t*>(p.x) + (size_t)(cta + 256 * wp) * 288 + l;
#pragma unroll
    for (int i = 0; i < 9; i++) { xr[i] = ld_nc(xs + 32 * i); xr[9 + i] = ld_nc(xs + 128 * 288 + 32 * i); }
  };
  if (rows && wg < 2) load_x();
  if (tid == 64 && cta == NCTA - 1) prefetch_l2(p.tab, sizeof(T_TAB));
  __syncwarp();
  auto tag_of = [](unsigned e) { return (e & 0x7fffu) | 0x8000u; };

  if (wg == 2) {
#pragma unroll
    for (int i = 0; i < 3; i++) {
      const float c0 = bf_lo(cv[i]), c1 = bf_hi(cv[i]);
      sts(red + 512 + min(t128 + 128 * i, 287) * 4, pack_bf16(__fdividef(c0, 1.0f + __expf(-c0)), __fdividef(c1, 1.0f + __expf(-c1))));
    }
    if (t128 == 0) sts(full0 + 248, ep0 + 1);
    if (wp == 9 && l < 11) asm volatile("prefetch.tensormap [%0];" ::"l"(&maps.z1 + l) : "memory");
    bar_sync(4, 128);
    if (mu < 72) {
      mod_unit(sc, mu, t128, sbase + O_P2, full0 + 8 * B_W0, 0, red, tag_of(upin(ep0) + 1));
      if (t128 == 0) TS(25);
    }
    CK(1);
  }
  const int pi = R / 15, col0 = 20 * (R - 15 * pi);
  const int xu = DF_ * pi + col0, xv = DF_ * (pi ? 16 - pi : 8) + col0;
  auto load_filter = [&](int a) {
    const int x = (a & 1) ? xv : xu;
    const bool wide = (x & 15) > 12;
    mbar_expect(full0 + 8 * B_FLT, wide ? 12288 : 8192);
    tma2d(sbase + O_RAW + a * 12288, &maps.wf[a & 2], x & ~15, 0, full0 + 8 * B_FLT);
    if (wide) tma2d(sbase + O_RAW + a * 12288 + 8192, &maps.wf[(a & 2) + 1], (x & ~15) + 32, 0, full0 + 8 * B_FLT);
  };
  const int kap = 8 * ((wp & 3) ^ (wg & 1)) + g;
  uint4 af[4];
  if (rows) {
    uint32_t tb[4];
#pragma unroll
    for (int i = 0; i < 4; i++) tb[i] = pack_bf16(tmat(cta, 8 * (i >> 1) + g, 2 * t + 8 * (i & 1)), tmat(cta, 8 * (i >> 1) + g, 2 * t + 8 * (i & 1) + 1));
    uint32_t sb1[3], lo[9];
#pragma unroll
    for (int i = 0; i < 4; i++) tb[i] = pin(tb[i]);
#pragma unroll
    for (int i = 0; i < 3; i++) {
      const int d = 48 * wp + 16 * i + (l & 15);
      sb1[i] = pin(sbase + O_B1 + (l >> 4) * 9216 + (d % 9) * 1024 + (d & 63) * 16);
    }
    const uint32_t snt = pin(sbase + O_NRM + ((l & 7) + 8 * (l >> 4)) * 1168 + (48 * wp + (l & 8)) * 2);
    uint2 ms[3], mc[3];
    const uint32_t smask = pin(t ? 0u : 0xffff0000u);
    const uint32_t* const mp = pin(sc->moda + (cta >> 4) * (2 * D_) + 48 * wp + 2 * g);
    auto load_mod = [&]() {
#pragma unroll
      for (int i = 0; i < 3; i++) { ms[i] = ld_rlx2(mp + 16 * i); mc[i] = ld_rlx2(mp + D_ + 16 * i); }
    };
    if (wg < 2) {
#pragma unroll
      for (int k1 = 0; k1 < 9; k1++) lo[k1] = pin(sbase + O_Z1 + line_off(k1, kap, 4 * wg + t, cta & 3));
      float a[18], b[18];
#pragma unroll
      for (int i = 0; i < 9; i++) { a[2 * i] = bf_lo(xr[i]); a[2 * i + 1] = bf_hi(xr[i]); b[2 * i] = bf_lo(xr[9 + i]); b[2 * i + 1] = bf_hi(xr[9 + i]); }
      float oa, ra, ob, rb;
      ln_stats2(a, b, 1.0f, oa, ra, ob, rb);
      CK(1);
      const uint32_t sn = sbase + O_NRM + wp * 2336 + l * 4;
#pragma unroll
      for (int i = 0; i < 9; i++) {
        sts(sn + i * 128, pack_bf16(fmaf(a[2 * i], ra, oa), fmaf(a[2 * i + 1], ra, oa)));
        sts(sn + 1168 + i * 128, pack_bf16(fmaf(b[2 * i], rb, ob), fmaf(b[2 * i + 1], rb, ob)));
      }
      CK(2);
      bar_arrive(10, NTHR);
      load_mod();
#pragma unroll
      for (int kk = 0; kk < 4; kk++) af[kk] = ld_nc4(p.tab + TB_F + kk * 128 + (t128 ^ (wg << 5)));
      bar_sync(1, 256);
      if (tid == 0) TS(2);
    } else {
      bar_sync(10, NTHR);
      load_mod();
      CK(2);
      if (PFF && wp >= 12 - PFF && elect()) prefetch_l2(reinterpret_cast<const uint8_t*>(wp == 10 ? p.wr : p.wi) + cta * 9248, 9248);
      __syncwarp();
    }
    float rs[3][8];
#pragma unroll
    for (int i = 0; i < 3; i++) {
      uint32_t a0, a1, a2, a3;
      asm volatile("ldmatrix.sync.aligned.m8n8.x4.trans.shared.b16 {%0,%1,%2,%3}, [%4];" : "=r"(a0), "=r"(a1), "=r"(a2), "=r"(a3)
                   : "r"(snt + 32 * i) : "memory");
      mma16<false>(&rs[i][0], a0, a1, a2, a3, tb[0], tb[1]);
      mma16<false>(&rs[i][4], a0, a1, a2, a3, tb[2], tb[3]);
    }
    CK(3);
    const uint32_t tag16 = tag_of(upin(ep0) + 1), tag1 = tag16 & 1;
    {
      int it = 0;
#pragma unroll 1
      while (true) {
        uint32_t bad = 0;
#pragma unroll
        for (int i = 0; i < 3; i++) bad |= diff2(ms[i].x, ms[i].y, tag16) | diff2(mc[i].x, mc[i].y, tag16);
        if (!any(bad & 0xffffu) || ++it > SPIN_MAX) break;
        load_mod();
      }
      CK(4);
      if (tid == 0) TS(3);
#pragma unroll
      for (int i = 0; i < 3; i++) {
        const float c0 = bf_hi(mc[i].x), c1 = bf_hi(mc[i].y);
        const float s0 = __uint_as_float(ms[i].x & smask), s1 = __uint_as_float(ms[i].y & smask);
        stmatrix4(sb1[i], pack_bf16(fmaf(rs[i][0], c0, s0), rs[i][1] * c0), pack_bf16(fmaf(rs[i][2], c1, s1), rs[i][3] * c1),
                  pack_bf16(rs[i][4] * c0, rs[i][5] * c0), pack_bf16(rs[i][6] * c1, rs[i][7] * c1));
      }
    }
    fence_async_smem();
    CK(5);
    if (wg == 2) {
      bar_arrive(5, NTHR);
      if (R >= 0 && elect()) load_filter(wp - 8);
      __syncwarp();
      const int slot = 4 * (cta & 7) + ((cta >> 4) & 3) + 32 * (2 * (cta >> 6) + ((cta >> 3) & 1));
      const uint32_t c0 = upin(40 * slot), c1 = upin(60 * (wp & 1)), src = upin(sbase + O_Z1 + (wp & 1) * 9600);
      const CUtensorMap* mz = upin(&maps.z1);
      unsigned* hint = pin(sc->cnt + C_Z1 + 32 * (wp & 1));
      if (wp < 10) {
        bar_sync(2 + (wp & 1), 160);
        if (elect()) tma_st2d(mz, src, c0, c1);
        bulk_commit_wait();
        if (elect()) red_add(hint, 1);
        if (tid == 256) TS(4);
        __syncwarp();
      }
    } else {
      bar_sync(5, NTHR);
      CK(6);
      float acc[36];
      const uint32_t db = (((sbase + O_B1 + wg * 9216) & 0x3FFFF) >> 4) | ((128 >> 4) << 16);
      wg_fence();
#pragma unroll
      for (int kk = 0; kk < 4; kk++) wgmma_rs_72(acc, af[kk].x, af[kk].y, af[kk].z, af[kk].w, db + kk * 16, 1024 >> 4, kk);
      wg_commit();
      wg_wait<0>();
      reg_fence(acc);
      CK(7);
      float2 za[9], zb[9];
#pragma unroll
      for (int i = 0; i < 9; i++) { za[i] = make_float2(acc[4 * i], acc[4 * i + 2]); zb[i] = make_float2(acc[4 * i + 1], acc[4 * i + 3]); }
      dft9(za); dft9(zb);
      if (kap == 0) {
#pragma unroll
        for (int k = 1; k < 5; k++) {
          float2 a = za[k], b = za[9 - k];
          za[k] = make_float2(a.x + b.x, a.y - b.y); za[9 - k] = make_float2(a.y + b.y, b.x - a.x);
          a = zb[k]; b = zb[9 - k];
          zb[k] = make_float2(a.x + b.x, a.y - b.y); zb[9 - k] = make_float2(a.y + b.y, b.x - a.x);
        }
        sts2(lo[0] + 288 * 8, set_tag(pack_bf16(za[0].y, 0.f), tag1), pack_bf16(zb[0].y, 0.f));
        za[0].y = 0.f; zb[0].y = 0.f;
      }
      __syncwarp();
#pragma unroll
      for (int k1 = 0; k1 < 9; k1++) sts2(lo[k1], set_tag(pack_bf16(za[k1].x, za[k1].y), tag1), pack_bf16(zb[k1].x, zb[k1].y));
      fence_async_smem();
      CK(8);
      bar_arrive(2 + wg, 160);
      {
        const uint32_t fx = (((cta >> 4) ^ cta) & 3) << 3, dl = O_IN - O_Z1, st = sbase + O_ST + 15360 + tid * 16;
        sts4(st, (lo[0] ^ fx) + dl, (lo[1] ^ fx) + dl, (lo[2] ^ fx) + dl, (lo[3] ^ fx) + dl);
        sts4(st + 4096, (lo[4] ^ fx) + dl, (lo[5] ^ fx) + dl, (lo[6] ^ fx) + dl, (lo[7] ^ fx) + dl);
        sts4(st + 8192, (lo[8] ^ fx) + dl, (lo[0] ^ fx) + dl + (kap ? 0 : 288 * 8),
             sbase + O_B3 + wg * 1024 + (l >> 4) * 2048 + (2 * (kap & 24) + (l & 15)) * 16, 0);
      }
    }
    {
      uint32_t sy[6];
#pragma unroll
      for (int i = 0; i < 6; i++) {
        const int rr = 16 * (wp & 3) + g + 8 * (i & 1);
        sy[i] = sbase + O_Y + (t * 584 + 64 * ((3 * wg + (i >> 1) + 63 - rr) % 9) + rr) * 4;
      }
      sts4(sbase + O_ST + tid * 16, movm(tb[0]), movm(tb[2]), movm(tb[1]), movm(tb[3]));
      sts4(sbase + O_ST + 6144 + tid * 16, sy[0], sy[1], sy[2], sy[3]);
      sts2(sbase + O_ST + 12288 + tid * 8, sy[4], sy[5]);
    }
  } else {
    __syncthreads();
  }

  const unsigned ep = upin(lds(full0 + 248));
  const uint32_t tag16 = tag_of(ep), tag1 = ep & 1;
  auto load_wm = [&](int u) {
    if (wp > 8 && elect()) {
      mbar_expect(full0 + 8 * B_WM, 6144);
      tma2d(sbase + O_NRM + (wp - 9) * 6144, &maps.wm, 16 * u, 192 * (wp - 9), full0 + 8 * B_WM);
    }
    __syncwarp();
  };
  if (R >= 0) {
    const int nl = (col0 + wp < DF_) + (wg < 2 && col0 + wp + 12 < DF_);
    uint4 cf[2][4], G[4];
#pragma unroll
    for (int i = 0; i < 4; i++) {
      cf[0][i] = __ldg(p.tab + TB_P2 + i * 32 + l);
      cf[1][i] = __ldg(p.tab + TB_P2 + (pi ? i : 4 + i) * 32 + l);
      G[i] = __ldg(p.tab + TB_P2 + (8 + i) * 32 + l);
    }
    const uint32_t* zin = sc->z1 + (size_t)R * 5120;
    if (wp == 10) {
      const uint32_t* zu = upin(zin);
      if (elect()) mbar_expect(full0 + 8 * B_Z1, 20480);
      wait_cnt(sc->cnt + C_Z1 + 32 * (pi >> 2), 128 * ep);
      if (elect()) {
        bulk_ld(sbase + O_P2, zu, 20480, full0 + 8 * B_Z1);
        TS(12);
      }
      __syncwarp();
    }
    mbar_wait(full0 + 8 * B_FLT, 0);
    CK(9);
    float wn[16], wc[16];
#pragma unroll 1
    for (int ln = nl - 1; ln >= 0; ln--) {
      const int col = col0 + wp + 12 * ln, k2 = (57 * col) & 63;
      const bool cj = k2 > 32 || (k2 == 32 && col != 288);
      const float nr = ((col & 31) == 0 && col != 0 && col != 288 ? 0.5f : 1.0f) / ((float)S_ * D_), ni = cj ? -nr : nr;
#pragma unroll
      for (int i = 0; i < 16; i++) wn[i] = wc[i];
#pragma unroll
      for (int cl = 0; cl < 2; cl++) {
        const int v = cl ^ (cj && pi), e = ((v ? xv : xu) & 15) + wp + 12 * ln, sh = e < 32 ? 6 : 5;
        const uint32_t base = sbase + O_RAW + v * 12288 + (e < 32 ? 2 * e : 8192 - 64 + 2 * e), msk = e < 32 ? 0x30 : 0x10;
        const int dm = v ? (cj || pi ? -1 : 0) : 0;
#pragma unroll
        for (int tt = 0; tt < 4; tt++) {
          const int kc = g + 64 * (tt >> 1) + 16 * t + 8 * (tt & 1);
          uint32_t a = base + ((((cj ? -kc : kc) + dm) & 127) << sh);
          a ^= (a >> 3) & msk;
          wc[4 * tt + 2 * cl] = lds_bf(a) * nr; wc[4 * tt + 2 * cl + 1] = lds_bf(a + 24576) * ni;
        }
      }
    }
    const float al = __uint_as_float(pin((pi ? 0x3f800000u : 0u) + (l >> 5)));
    const uint32_t tagv = pin(tag1 + (l >> 5));
    CK(10);
    uint32_t off = pin(l * 160 + ((wp ^ (g & 3)) << 3));
    uint32_t offo = pin(sbase + O_P2 + 20480 + off - 64 * l), po = 3072;
    unsigned* hz2 = pin(sc->cnt + C_Z2);
    const uint32_t do2 = pin(12288 - 32 * l);
    const CUtensorMap* mz2 = upin(&maps.z2[wp == 0]);
    const uint32_t sz2 = upin(sbase + O_P2 + 20480 + (wp ? 0 : 12288)), cz2 = upin(40 * R + (wp ? 0 : 24));
    mbar_wait(full0 + 8 * B_Z1, 0);
    CK(11);
    if (tid == 0) TS(8);
    if (wg == 2) load_wm(72 + mu);
    uint2 v[4], v2[4];
    const uint32_t o2 = nl > 1 ? 96 : 0;
#pragma unroll
    for (int i = 0; i < 4; i++) { v[i] = lds2(sbase + O_P2 + off + i * 5120); v2[i] = lds2(sbase + O_P2 + off + o2 + i * 5120); }
    auto bad2 = [&]() {
      return any(or3(or3(diff2(v[0].x, v[1].x, tagv), diff2(v[2].x, v[3].x, tagv), diff2(v2[0].x, v2[1].x, tagv)), diff2(v2[2].x, v2[3].x, tagv), 0) & 1);
    };
    if (__builtin_expect(bad2() && nl, 0)) {
      FAILCNT(0);
      int it = 0;
      do {
#pragma unroll
        for (int i = 0; i < 4; i++) {
          v[i] = ld_rlx2(reinterpret_cast<const uint8_t*>(zin) + off + i * 5120);
          v2[i] = ld_rlx2(reinterpret_cast<const uint8_t*>(zin) + off + o2 + i * 5120);
        }
      } while (bad2() && ++it < SPIN_MAX);
    }
#pragma unroll 1
    for (int ln = 0; ln < nl; ln++, offo += do2, po = 2048) {
      float d[4][4];
      uint32_t A[8];
#pragma unroll
      for (int h = 0; h < 2; h++) {
        mma16<false>(d[2 * h], cf[0][0].x, cf[0][0].y, cf[0][0].z, cf[0][0].w, v[h].x, v[2 + h].x);
        mma16<false>(d[2 * h + 1], cf[1][0].x, cf[1][0].y, cf[1][0].z, cf[1][0].w, v[h].y, v[2 + h].y);
      }
      if (ln) { fence_async_smem(); bar_arrive(15, NTHR); }
#pragma unroll
      for (int h = 0; h < 2; h++)
#pragma unroll
        for (int L = 0; L < 2; L++) {
          const uint4 tw = cf[L][2 + h];
          const float* z = d[2 * h + L];
          const float2 z0 = cmul(make_float2(z[0], z[2]), make_float2(__uint_as_float(tw.x), __uint_as_float(tw.y)));
          const float2 z1 = cmul(make_float2(z[1], z[3]), make_float2(__uint_as_float(tw.z), __uint_as_float(tw.w)));
          A[4 * h + L] = pack_bf16(z0.x, z0.y); A[4 * h + 2 + L] = pack_bf16(z1.x, z1.y);
        }
#pragma unroll
      for (int tt = 0; tt < 4; tt++) {
        mma16<false>(d[tt], A[0], A[1], A[2], A[3], G[tt].x, G[tt].y);
        mma16<true>(d[tt], A[4], A[5], A[6], A[7], G[tt].z, G[tt].w);
      }
#pragma unroll
      for (int tt = 0; tt < 4; tt++) {
        const float ar = d[tt][0], aj = d[tt][1], br = d[tt][2], bj = d[tt][3];
        const float2 y1 = cmul(make_float2(fmaf(-al, bj, ar), fmaf(al, br, aj)), make_float2(wc[4 * tt], wc[4 * tt + 1]));
        const float2 y2 = cmul(make_float2(fmaf(al, ar, bj), fmaf(al, aj, -br)), make_float2(wc[4 * tt + 2], wc[4 * tt + 3]));
        A[2 * tt] = pack_bf16(fmaf(al, y2.x, y1.x), fmaf(-al, y2.y, -y1.y));
        A[2 * tt + 1] = pack_bf16(fmaf(al, y1.y, -y2.y), fmaf(al, y1.x, -y2.x));
      }
#pragma unroll
      for (int i = 0; i < 16; i++) wc[i] = wn[i];
#pragma unroll
      for (int i = 0; i < 4; i++) v[i] = v2[i];
#pragma unroll
      for (int tt = 0; tt < 4; tt++) {
        mma16<false>(d[tt], A[0], A[1], A[2], A[3], G[tt].x, G[tt].y);
        mma16<true>(d[tt], A[4], A[5], A[6], A[7], G[tt].z, G[tt].w);
      }
#pragma unroll
      for (int h = 0; h < 2; h++)
#pragma unroll
        for (int L = 0; L < 2; L++) {
          const uint4 tw = cf[L][2 + h];
          const float2 z0 = cmul(make_float2(d[2 * h][2 * L], d[2 * h][2 * L + 1]), make_float2(__uint_as_float(tw.x), __uint_as_float(tw.y)));
          const float2 z1 = cmul(make_float2(d[2 * h + 1][2 * L], d[2 * h + 1][2 * L + 1]), make_float2(__uint_as_float(tw.z), __uint_as_float(tw.w)));
          A[4 * h + 2 * L] = movm(pack_bf16(z0.x, z1.x)); A[4 * h + 2 * L + 1] = movm(pack_bf16(z0.y, z1.y));
        }
#pragma unroll
      for (int h = 0; h < 2; h++) {
        mma16<false>(d[0], cf[0][1].x, cf[0][1].y, cf[0][1].z, cf[0][1].w, A[4 * h], A[4 * h + 1]);
        mma16<false>(d[1], cf[1][1].x, cf[1][1].y, cf[1][1].z, cf[1][1].w, A[4 * h + 2], A[4 * h + 3]);
#pragma unroll
        for (int e = 0; e < 2; e++)
          sts2(offo + (2 * h + e) * po, set_tag(pack_bf16(d[0][e], d[0][2 + e]), tagv), pack_bf16(d[1][e], d[1][2 + e]));
      }
      CK(12 + ln);
    }
    fence_async_smem();
    if (nl < 2 && wp != 8) bar_arrive(15, NTHR);
    if (wp & 7) { if (wg < 2) bar_arrive(6, 256); }
    else {
      if (wp) bar_sync(15, NTHR); else bar_sync(6, 256);
      if (elect()) tma_st2d(mz2, sz2, cz2, 0);
      bulk_commit_wait();
      if (wp == 0 && elect()) red_add(hz2, 1);
      if (tid == 0) TS(9);
      __syncwarp();
    }
  }
  if (wg == 2) {
#pragma unroll 1
    for (int u = 72 + mu, k = 0; u < 216; u += NCTA, k ^= 1) {
      if (R < 0) { fence_async_smem(); bar_sync(4, 128); load_wm(u); }
      mod_unit(sc, u, t128, sbase + O_NRM, full0 + 8 * B_WM, k, red + 256 - 256 * k, tag16);
    }
    fence_async_smem();
    CK(13);
  }

  const int grp = bx / 11, m1 = bx - 11 * grp;
  const bool helper = (m1 & 3) == 3;
  const int f1 = 384 * grp + (helper ? 192 : 128) * (m1 >> 2);
  const int d1 = 160 * (m1 & 3), flip = m1 >= 7;
  const int a1bytes = helper ? 24576 : 16384;
  auto load_a1 = [&](int st, int kb) {
    mbar_expect(full0 + 8 * st, a1bytes);
    tma4d_ef(sbase + st * STAGE, helper ? &maps.w1b : &maps.w1a, 4 * (kb >> 3), 16 * (kb & 7), f1 >> 6, full0 + 8 * st);
  };

  if (rows) {
#pragma unroll
    for (int kk = 0; kk < 4; kk++) af[kk] = __ldg(p.tab + TB_E + kk * 128 + t128);
    const uint4 c0 = lds4(sbase + O_ST + tid * 16), c1 = lds4(sbase + O_ST + 6144 + tid * 16);
    const uint2 c2 = lds2(sbase + O_ST + 12288 + tid * 8);
    const uint32_t tb[4] = {c0.x, c0.y, c0.z, c0.w}, sy[6] = {c1.x, c1.y, c1.z, c1.w, c2.x, c2.y};
    const uint32_t l8 = pin(8 * l), syl = pin(sbase + O_Y + wp * 2336 + 8 * l);
    uint32_t sh3[3], ham[3];
#pragma unroll
    for (int k = 0; k < 3; k++) {
      const int pos = k && (l >> 4) == k - 1 ? (l & 8) + 4 * (l & 1) + ((l >> 1) & 3) : 4 * (l & 3) + ((l >> 2) & 3);
      const int sw = 2 * cta + (wp & 1), ph = pos ^ ((sw & 3) << 2);
      sh3[k] = pin((wp < 2 ? (l >> 4) * 4096 : sbase + O_B3 + (wp >> 1) * 4608 + (l >> 4) * 256) + (wp & 1) * 128 + ph * 4);
      const bool tg = ((ph ^ sw) & 7) == 0;
      ham[k] = pin(tg ? ~1u : ~0u);
    }
    uint8_t* const h3g = upin(sc->h3 + (cta >> 4) * (18 * 4096) + (cta & 15) * 256);
    const int slot = 4 * (cta >> 4) + ((cta >> 1) & 3) + 32 * (2 * ((cta >> 3) & 1) + (cta & 1));
    const uint32_t* zin = sc->z2 + (size_t)slot * 4800;
    uint32_t ga[9];
    uint2 sh[9], sw[9];
    auto load_mod3 = [&](int part) {
#pragma unroll
      for (int i = 0; i < 9; i++) {
        if (part != 2) { const uint2 v = lds2(l8 + sbase + O_MOD + 256 * i); ga[i] = __byte_perm(v.x, v.y, 0x7632); }
        if (part != 1) { sh[i] = lds2(l8 + sbase + O_MOD + 4 * D_ + 256 * i); sw[i] = lds2(l8 + sbase + O_MOD + 8 * D_ + 256 * i); }
      }
    };
    if (wg == 2) {
      {
        uint4 v[4];
        const int i3 = min(t128 + 384, 431);
        int it = 0;
        while (true) {
          uint32_t bad = 0;
#pragma unroll
          for (int k = 0; k < 4; k++) v[k] = ld_rlx4(sc->mod + 4 * (k < 3 ? t128 + 128 * k : i3));
#pragma unroll
          for (int k = 0; k < 4; k++) {
            v[k].x ^= tag16; v[k].y ^= tag16; v[k].z ^= tag16; v[k].w ^= tag16;
            bad |= v[k].x | v[k].y | v[k].z | v[k].w;
          }
          if (!any(bad & 0xffffu) || ++it > SPIN_MAX) break;
        }
#pragma unroll
        for (int k = 0; k < 4; k++) sts4(sbase + O_MOD + 16 * (k < 3 ? t128 + 128 * k : i3), v[k].x, v[k].y, v[k].z, v[k].w);
      }
      CK(14);
      bar_sync(10, NTHR);
      mbar_wait(full0 + 8 * B_Z2, 0);
      if (elect()) {
        load_a1(wp - 8, wp - 8);
        if (wp > 8 && wp - 8 < NG1) prefetch_l2(reinterpret_cast<const uint8_t*>(p.w1) + (size_t)(128 * (4 * ((wp - 8) >> 1) + (cta >> 5)) + 64 * (wp & 1) + 2 * (cta & 31)) * (2 * F_), 4 * F_);
      }
      __syncwarp();
    } else {
      const uint4 e0 = lds4(sbase + O_ST + 15360 + tid * 16), e1 = lds4(sbase + O_ST + 19456 + tid * 16), e2 = lds4(sbase + O_ST + 23552 + tid * 16);
      const uint32_t lo[9] = {e0.x, e0.y, e0.z, e0.w, e1.x, e1.y, e1.z, e1.w, e2.x}, lx = e2.y, sb3 = e2.z;
      if (MODPOS == 0) bar_arrive(10, NTHR);
      CK(14);
      if (wp == 1) {
        const uint32_t* zu = upin(zin);
        if (elect()) mbar_expect(full0 + 8 * B_Z2, 19200);
        wait_cnt(sc->cnt + C_Z2, 120 * ep);
        if (elect()) {
          bulk_ld(sbase + O_IN, zu, 19200, full0 + 8 * B_Z2);
          TS(14);
        }
        __syncwarp();
      }
      if (MODPOS) { bar_sync(10, NTHR); load_mod3(MODPOS - 1); }
      mbar_wait(full0 + 8 * B_Z2, 0);
      CK(15);
      if (tid == 0) TS(11);
      uint2 v[10];
#pragma unroll
      for (int k1 = 0; k1 < 10; k1++) v[k1] = lds2(k1 < 9 ? lo[k1] : lx);
      auto bad3 = [&]() {
        return any(or3(or3(diff2(v[0].x, v[1].x, tag1), diff2(v[2].x, v[3].x, tag1), diff2(v[4].x, v[5].x, tag1)), diff2(v[6].x, v[7].x, tag1), diff2(v[8].x, v[9].x, tag1)) & 1);
      };
      if (__builtin_expect(bad3(), 0)) {
        FAILCNT(1);
        int it = 0;
        do {
#pragma unroll
          for (int k1 = 0; k1 < 10; k1++) v[k1] = ld_rlx2(reinterpret_cast<const uint8_t*>(zin) + ((k1 < 9 ? lo[k1] : lx) - (sbase + O_IN)));
        } while (bad3() && ++it < SPIN_MAX);
      }
      float2 za[9], zb[9];
#pragma unroll
      for (int i = 0; i < 9; i++) { za[i] = make_float2(bf_lo(v[i].x), bf_hi(v[i].x)); zb[i] = make_float2(bf_lo(v[i].y), bf_hi(v[i].y)); }
      if (kap == 0) {
#pragma unroll
        for (int k = 1; k < 5; k++) {
          float2 a = za[k], b = za[9 - k];
          za[k] = make_float2(a.x - b.y, a.y + b.x); za[9 - k] = make_float2(a.x + b.y, b.x - a.y);
          a = zb[k]; b = zb[9 - k];
          zb[k] = make_float2(a.x - b.y, a.y + b.x); zb[9 - k] = make_float2(a.x + b.y, b.x - a.y);
        }
        za[0].y = bf_lo(v[9].x); zb[0].y = bf_lo(v[9].y);
      }
      __syncwarp();
      dft9(za); dft9(zb);
#pragma unroll
      for (int n = 0; n < 8; n += 2) {
        const int i0 = (9 - n) % 9, i1 = 8 - n;
        stmatrix4(sb3 + n * 2048, pack_bf16(za[i0].x, zb[i0].x), pack_bf16(za[i0].y, zb[i0].y), pack_bf16(za[i1].x, zb[i1].x), pack_bf16(za[i1].y, zb[i1].y));
      }
      stmatrix2(sb3 + 8 * 2048, pack_bf16(za[1].x, zb[1].x), pack_bf16(za[1].y, zb[1].y));
      fence_async_smem();
    }
    CK(16);
    __syncthreads();
    CK(17);
    float acc[24];
    const uint32_t db = (((sbase + O_B3 + wg * 6144) & 0x3FFFF) >> 4) | ((128 >> 4) << 16);
    wg_fence();
#pragma unroll
    for (int kk = 0; kk < 4; kk++) wgmma_rs_48(acc, af[kk].x, af[kk].y, af[kk].z, af[kk].w, db + kk * 16, 1024 >> 4, kk);
    wg_commit();
    if (wg < 2 && MODPOS == 0) load_mod3(0);
    wg_wait<0>();
    reg_fence(acc);
    CK(18);
#pragma unroll
    for (int i = 0; i < 3; i++) {
      const float* a = &acc[8 * i];
      const uint32_t a0 = pack_bf16(a[0], a[1]), a1 = pack_bf16(a[2], a[3]), a2 = pack_bf16(a[4], a[5]), a3 = pack_bf16(a[6], a[7]);
#pragma unroll
      for (int jh = 0; jh < 2; jh++) {
        float y[4];
        mma16<false>(y, a0, a1, a2, a3, tb[2 * jh], tb[2 * jh + 1]);
        sts(sy[2 * i] + jh * (4 * 584 * 4), pack_bf16(y[0], y[1]));
        sts(sy[2 * i + 1] + jh * (4 * 584 * 4), pack_bf16(y[2], y[3]));
      }
    }
    CK(19);
    if (wg == 2) { bar_arrive(7, NTHR); bar_sync(15, NB15); }
    else {
      bar_sync(7, NTHR);
      if ((LNM >> wp) & 1) bar_sync(15, NB15);
      CK(20);
      float a[18], b[18];
#pragma unroll
      for (int i = 0; i < 9; i++) {
        const uint2 y = lds2(syl + 256 * i);
        xr[i] = hfma2(ga[i], __byte_perm(y.x, y.y, 0x5410), xr[i]);
        xr[9 + i] = hfma2(ga[i], __byte_perm(y.x, y.y, 0x7632), xr[9 + i]);
        a[2 * i] = bf_lo(xr[i]); a[2 * i + 1] = bf_hi(xr[i]); b[2 * i] = bf_lo(xr[9 + i]); b[2 * i + 1] = bf_hi(xr[9 + i]);
      }
      float oa, ra, ob, rb;
      if (MODPOS == 2) load_mod3(2);
      ln_stats2(a, b, 1.0f, oa, ra, ob, rb);
      CK(21);
#pragma unroll
      for (int i = 0; i < 9; i++) {
        const float c0 = __uint_as_float(sw[i].x), c1 = __uint_as_float(sw[i].y), s0 = __uint_as_float(sh[i].x), s1 = __uint_as_float(sh[i].y);
        a[2 * i] = fmaf(fmaf(a[2 * i], ra, oa), c0, s0); a[2 * i + 1] = fmaf(fmaf(a[2 * i + 1], ra, oa), c1, s1);
        b[2 * i] = fmaf(fmaf(b[2 * i], rb, ob), c0, s0); b[2 * i + 1] = fmaf(fmaf(b[2 * i + 1], rb, ob), c1, s1);
      }
      ln_stats2(a, b, 0.5f, oa, ra, ob, rb);
      CK(22);
      if (wp < 2) bar_arrive(15, NB15);
      uint32_t hv[18];
#pragma unroll
      for (int i = 0; i < 9; i++) {
        const int k = i == 2 ? 1 : i == 6 ? 2 : 0;
        hv[2 * i] = bitsel(pack_bf16(fmaf(a[2 * i], ra, oa), fmaf(a[2 * i + 1], ra, oa)), ham[k], tag1);
        hv[2 * i + 1] = bitsel(pack_bf16(fmaf(b[2 * i], rb, ob), fmaf(b[2 * i + 1], rb, ob)), ham[k], tag1);
      }
      if (wp < 2) {
#pragma unroll
        for (int i = 0; i < 18; i++) {
          const int k = (i >> 1) == 2 ? 1 : (i >> 1) == 6 ? 2 : 0;
          asm volatile("st.global.b32 [%0], %1;" ::"l"(h3g + sh3[k] + (i >> 1) * 8192 + (i & 1) * 64), "r"(hv[i]) : "memory");
        }
        if (elect()) red_add(sc->cnt + C_H3 + (cta >> 4), 1);
        if (tid == 0) TS(13);
      } else {
#pragma unroll
        for (int i = 0; i < 18; i++) sts(sh3[(i >> 1) == 2 ? 1 : (i >> 1) == 6 ? 2 : 0] + (i >> 1) * 512 + (i & 1) * 64, hv[i]);
        fence_async_smem();
      }
      bar_arrive(9, 288);
      CK(23);
    }
  }

  const bool g2 = rows;
  const int z2 = cta, r = z2 >> 6;
  const int s2 = 128 * ((z2 >> 2) & 15), d2 = 144 * (z2 & 3);
  constexpr int ST0 = (32 - JSK - 1) % NST, ST1 = 31 % NST;

  if (wg == 2) {
    asm volatile("setmaxnreg.dec.sync.aligned.u32 40;");
    auto load_b = [&](bool second, int i, int st) {
      const uint32_t lb = full0 + 8 * (B_LAND + st), bytes = second ? 18432 : STAGE - a1bytes;
      mbar_expect(lb, bytes);
      bulk_ld(sbase + (second ? st * STAGE2 + 16384 : st * STAGE + a1bytes),
              second ? sc->u + ((size_t)(36 * r + kb2_order(i)) * D_ + d2) * 128 : sc->h3 + ((size_t)(i * 18 + (d1 >> 5)) << 12), bytes, lb);
    };
    if (wp == 8) {
      int st = rows ? 4 : 0, ph = 1;
#pragma unroll 1
      for (int kb = st; kb < 32; kb++) {
        if (rows && (kb >> 1) == 2) mbar_wait(full0 + 8 * (B_S4 - 4 + kb), 0);
        mbar_wait(empty0 + 8 * st, ph);
        if (elect()) {
          load_a1(st, kb);
          if (kb >= PF2K && kb < PF2K + PF2 && g2)
            prefetch_l2(reinterpret_cast<const uint8_t*>(p.w2) + (size_t)(36 * r + kb2_order(kb - PF2K)) * 262144 + (z2 & 63) * 4096, 4096);
        }
        __syncwarp();
        ring_next<false>(st, ph);
      }
      if (g2) {
        st++;
#pragma unroll 1
        for (int i = 0; i < 36; i++) {
          if (i == HOLDA) mbar_wait(full0 + 8 * B_GO, 0);
          mbar_wait(empty0 + 8 * st, ph);
          if (elect()) {
            mbar_expect(full0 + 8 * st, 16384);
            tma3d_ef(sbase + st * STAGE2, &maps.w2, 64 * (36 * r + kb2_order(i)), s2 >> 6, full0 + 8 * st);
          }
          __syncwarp();
          ring_next<true>(st, ph);
        }
      }
    } else if (wp >= 10) {
      const int sw = wp - 10;
      if (sw) {
        if (rows) {
          bar_sync(9, 288);
          mbar_wait(full0 + 8 * H3W, 0);
          if (elect()) { tma_st3d(&maps.h3, sbase + O_B3 + 4608, 64 * (cta & 15), 18 * (cta >> 4), 1); mbar_arrive(full0 + 8 * B_S4); }
          bulk_commit_wait();
          if (elect()) {
            red_add(sc->cnt + C_H3 + (cta >> 4) + 8, 2);
            mbar_arrive(full0 + 8 * B_S5); mbar_arrive(full0 + 8 * B_S5);
            TS(24);
            asm volatile("fence.acq_rel.gpu;" ::: "memory");
            red_add(&sc->cnt[C_X + 64], 1);
          }
          __syncwarp();
        }
        if (g2) {
          uint2 v[3];
          int it = 0;
          do {
#pragma unroll
            for (int i = 0; i < 3; i++) v[i] = ld_rlx2(sc->mod + 3 * D_ + d2 + 2 * min(l + 32 * i, 71));
          } while (any(or3(diff2(v[0].x, v[0].y, tag16), diff2(v[1].x, v[1].y, tag16), diff2(v[2].x, v[2].y, tag16)) & 0xffffu) && ++it < SPIN_MAX);
#pragma unroll
          for (int i = 0; i < 3; i++) sts(sbase + O_GB + 4 * min(l + 32 * i, 71), __byte_perm(v[i].x, v[i].y, 0x7632));
          __syncwarp();
        }
        wait_cnt<true>(&sc->cnt[C_X + 64], 128 * ep);
        if (elect()) mbar_arrive(full0 + 8 * B_X);
        __syncwarp();
      }
      uint32_t lph = 0;
      auto check_tiles = [&](bool second, int n, int st, uint32_t o1, uint32_t d2nd) {
        const uint32_t b1 = pin(sbase + o1), b2 = pin(sbase + o1 + d2nd);
        int i = 0, it = 0;
#pragma unroll 1
        do {
          const uint32_t so = st * (second ? STAGE2 : STAGE);
          mbar_wait(full0 + 8 * (B_LAND + st), (lph >> st) & 1);
          lph ^= 1u << st;
          uint32_t v[20];
#pragma unroll
          for (int k = 0; k < 20; k++) if (!second || k < 10 || k >= 12) v[k] = lds(k < 12 ? b1 + so + k * 1024 : b2 + so + (k - 12) * 1024); else v[k] = tag1;
#pragma unroll
          for (int k = 0; k < 10; k++) v[k] = diff2(v[2 * k], v[2 * k + 1], tag1);
          const uint32_t bad = or3(or3(or3(v[0], v[1], v[2]), or3(v[3], v[4], v[5]), v[6]), v[7], or3(v[8], v[9], 0));
          if (__builtin_expect(any(bad & 1) && ++it < SPIN_MAX, 0)) {
            FAILCNT(2 + second);
            fence_async_smem();
            __syncwarp();
            if (elect()) load_b(second, i, st);
            __syncwarp();
            continue;
          }
          if (elect()) mbar_arrive(full0 + 8 * st);
          if (++st == NST) st = 0;
          i++;
        } while (i < n);
      };
      if (!sw) check_tiles(false, NV1, 0, a1bytes + l * 32 + (l >> 2) * 4, helper ? 4096 : 12288);
      const bool first = helper || m1 < W0N;
#pragma unroll 1
      for (int k = sw ? first : !first; k <= sw; k++) {
        const uint32_t stg = sbase + (!k ? ST0 * STAGE : helper ? ST1 * STAGE : O_U1);
        const int kbA = (f1 >> 6) + (helper ? 2 : 1) * (k ^ flip), kbB = helper ? (f1 >> 6) + 1 : kbA;
        uint8_t* const uA = upin(sc->u + ((size_t)kbA * D_ + d1) * 128);
        uint8_t* const uB = upin(sc->u + ((size_t)kbB * D_ + (helper ? d1 : d1 + 96)) * 128);
        unsigned* const fA = pin(sc->cnt + C_U + kb2_pos(kbA));
        unsigned* const fB = pin(sc->cnt + C_U + kb2_pos(kbB));
        const bool slow = sw && !helper;
        bar_sync(11 + k, 160);
        if (!slow) { if (elect()) { bulk_st(uA, stg, 96 * 128); TS(k ? 31 : 30); } __syncwarp(); }
        bar_sync(13 + k, 160);
        if (slow) {
          if (g2) mbar_wait(full0 + 8 * B_GO, 0);
          if (first) pause(10 * TRK0);
#pragma unroll 1
          for (int i = 0; i < 20480; i += 2048) {
            if (elect()) bulk_st(uA + i, stg + i, 2048);
            pause(k ? TRKC : TRK0);
          }
        }
        if ((helper ? k : !slow) && elect()) bulk_st(uB, stg + 96 * 128, helper ? 96 * 128 : 64 * 128);
        bulk_commit_wait();
        if (elect()) { red_add(fA, 1); if (helper && k) red_add(fB, 1); }
        if (elect()) {
          if (!k || helper) mbar_arrive(empty0 + 8 * (k ? ST1 : ST0));
          TS(k ? 23 : 17);
          mbar_arrive(full0 + 8 * B_S5);
        }
        __syncwarp();
      }
      if (sw) {
        mbar_wait(full0 + 8 * B_S5, rows);
        if (elect()) { asm volatile("fence.acq_rel.gpu;" ::: "memory"); red_add(&sc->cnt[C_X], 1); }
        __syncwarp();
      }
      if (g2) {
        if (!sw) check_tiles(true, NV2, 3, 16384 + l * 32 + (4 * (g & 1) + (g >> 1)) * 4, 10240);
        else {
          wait_cnt<true>(&sc->cnt[C_X], NCTA * ep);
          if (elect()) {
            mbar_arrive(full0 + 8 * B_X);
            if (cta == 0) sc->cnt[C_EP] = ep;
          }
          __syncwarp();
        }
      }
      __syncwarp();
    } else {
      uint32_t ready = 0;
      int st = 0, ph = 1;
#pragma unroll 1
      for (int kb = 0; kb < 32; kb++) {
        const uint8_t* src = upin(sc->h3 + ((size_t)(kb * 18 + (d1 >> 5)) << 12));
        const uint32_t dst = upin(sbase + st * STAGE + a1bytes), lb = full0 + 8 * ((kb < NV1 ? B_LAND : 0) + st);
        if (kb == NV1) { mbar_wait(full0 + 8 * B_X, 0); fence_async_glb(); ready = ~0u; }
        if (rows && (kb >> 1) == 2) mbar_wait(full0 + 8 * (B_S4 - 4 + kb), 0);
        mbar_wait(empty0 + 8 * st, ph);
        if (elect()) mbar_expect(lb, STAGE - a1bytes);
        wait_flags(sc->cnt + C_H3 + l, (kb & 7) + (kb < 8 ? 0 : 8), 32 * ep, ready);
        if (elect()) bulk_ld(dst, src, STAGE - a1bytes, lb);
        ring_next<false>(st, ph);
      }
      if (g2) {
        ready = 0;
        st++;
#pragma unroll 1
        for (int i = 0; i < 36; i++) {
          const int kb = kb2_order(i);
          const uint8_t* src = upin(sc->u + ((size_t)(36 * r + kb) * D_ + d2) * 128);
          const uint32_t dst = upin(sbase + st * STAGE2 + 16384), lb = full0 + 8 * ((i < NV2 ? B_LAND : 0) + st);
          if (i == NV2) { mbar_wait(full0 + 8 * B_X, 1); fence_async_glb(); ready = ~0u; }
          mbar_wait(empty0 + 8 * st, ph);
          if (elect()) mbar_expect(lb, 18432);
          wait_flags(sc->cnt + C_U + 64 * r + l, i & 31, 4 * ep, ready);
          if (elect()) {
            bulk_ld(dst, src, 18432, lb);
            if (i == GOAT) mbar_arrive(full0 + 8 * B_GO);
          }
          ring_next<true>(st, ph);
        }
      }
    }
  } else {
    asm volatile("setmaxnreg.inc.sync.aligned.u32 232;");
    const int wgu = wg;
    constexpr uint32_t sb4 = sbase >> 4;
    const int w = wp & 3;
    Ring rg = {0, 0};
    uint32_t* const x1p = p.out + (size_t)(cta + 256 * wp) * 288 + l;
    const uint32_t ad = pin(sbase + (!wg ? ST0 * STAGE : helper ? ST1 * STAGE : O_U1) + (8 * (l >> 4) + (l & 7)) * 128 + (((2 * w + ((l >> 3) & 1)) ^ (l & 7)) << 4));
    const uint32_t uam = pin(g == 2 * t ? 0xfffefffeu : ~0u), uom = tag1 * 0x10001u;
    float acc[96];
    constexpr uint32_t LA = (8192 >> 4) << 16, LB = (4096 >> 4) << 16;
    {
      const int fa = f1 + (helper ? 128 : 64) * (wg ^ flip) + 16 * w + g, fb = helper ? f1 + 64 + 16 * w + g : fa;
      const float a0 = 0.5f * __bfloat162float(p.b1[fa]), a1 = 0.5f * __bfloat162float(p.b1[fa + 8]);
      const float b0 = 0.5f * __bfloat162float(p.b1[fb]), b1 = 0.5f * __bfloat162float(p.b1[fb + 8]);
#pragma unroll
      for (int i = 0; i < 96; i++) acc[i] = i < 48 ? ((i & 2) ? a1 : a0) : ((i & 2) ? b1 : b0);
      reg_fence(acc);
    }
    if (!helper) gemm_main<0>(acc, sb4 + (wgu ^ flip) * 512 + LA, 0, sb4 + 1024 + LB, wgu, rg, rows, x1p, xr);
    else {
      float ac2[96];
#pragma unroll
      for (int i = 0; i < 96; i++) asm volatile("mov.b32 %0, %1;" : "=f"(ac2[i]) : "f"(acc[i]));
      gemm_main<1>(ac2, sb4 + (wgu ^ flip) * 1024 + LA, sb4 + 512 + LA, sb4 + 1536 + LB, wgu, rg, rows, x1p, xr);
#pragma unroll
      for (int i = 0; i < 96; i++) asm volatile("mov.b32 %0, %1;" : "=f"(acc[i]) : "f"(ac2[i]));
    }
    if (t128 == 0) { TS(wg ? 16 : 6); if (wg) TSC(5); }
    {
      float tp[2] = {0.f, 0.f};
#pragma unroll
      for (int j = 0; j < 12; j++) {
        const float* a = &acc[8 * j];
        const float k3 = j < 2 ? GK3 : fmaf(tp[j & 1], 0.0f, GK3);
        float o[8];
#pragma unroll
        for (int e = 0; e < 8; e++) {
          float z = a[e] * fmaf(a[e] * k3, a[e], GK1);
          asm("tanh.approx.f32 %0, %0;" : "+f"(z));
          if (e == GDEP) tp[j & 1] = z;
          o[e] = fmaf(a[e], z, a[e]);
        }
        stmatrix4t(ad + j * 2048, bitsel(pack_bf16(o[0], o[1]), uam, uom), pack_bf16(o[2], o[3]), bitsel(pack_bf16(o[4], o[5]), uam, uom), pack_bf16(o[6], o[7]));
        if (j == 5) {
          fence_async_smem();
          bar_arrive(11 + wgu, 160);
        }
        if ((j == 5 && helper && !wgu) || (j == 9 && !helper)) break;
      }
      fence_async_smem();
      bar_arrive(13 + wgu, 160);
      if (t128 == 0) TS(wg ? 29 : 28);
    }
    if (g2) {
      const int mb = wgu ^ r;
      const int odd = z2 & 1;
      uint4 gq[4];
      uint2 gs;
      {
        float a0 = 0.f, a1 = 0.f;
        if (wgu) { a0 = __bfloat162float(p.b2[s2 + 64 * mb + 16 * w + g]); a1 = __bfloat162float(p.b2[s2 + 64 * mb + 16 * w + 8 + g]); }
#pragma unroll
        for (int i = 0; i < 4; i++) gq[i] = lds4(sbase + O_GB + 32 * odd + 64 * i + 16 * t);
        gs = lds2(sbase + O_GB + (odd ? 0 : 256) + 8 * t);
#pragma unroll
        for (int i = 0; i < 72; i++) acc[i] = (i & 2) ? a1 : a0;
      }
      uint32_t* const ob = p.out + (size_t)(s2 + 64 * mb + 16 * w + g) * 288 + (d2 >> 1);
      uint32_t* const oq = pin(ob + 8 * odd + 4 * t);
      uint32_t* const os = pin(ob + (odd ? 0 : 64) + 2 * t);
      rg.st++;
      gemm_main<3>(acc, sb4 + mb * 512 + LA, 0, sb4 + 1024 + (1 << 16), wgu, rg, rows, x1p, xr);
      if (t128 == 0) { TS(wg ? 20 : 19); if (wg) TSC(22); }
      auto finish = [&](const float* aq, const float* as) {
#pragma unroll
        for (int i = 0; i < 8; i++) {
          const float* a = aq + 16 * (i >> 1) + 2 * (i & 1);
          const uint4 gv = gq[i >> 1];
          red_bf16x8(oq + (i & 1) * 2304 + 16 * (i >> 1), hmul2(gv.x, pack_bf16(a[0], a[1])), hmul2(gv.y, pack_bf16(a[4], a[5])),
                     hmul2(gv.z, pack_bf16(a[8], a[9])), hmul2(gv.w, pack_bf16(a[12], a[13])));
        }
#pragma unroll
        for (int i = 0; i < 2; i++) red_bf16x4(os + i * 2304, hmul2(gs.x, pack_bf16(as[2 * i], as[2 * i + 1])), hmul2(gs.y, pack_bf16(as[2 * i + 4], as[2 * i + 5])));
      };
      if (odd) finish(&acc[8], &acc[0]); else finish(&acc[0], &acc[64]);
      if (t128 == 0) TS(wg ? 7 : 21);
      __syncwarp();
    }
  }
}

typedef CUresult (*EncodeFn)(CUtensorMap*, CUtensorMapDataType, cuuint32_t, void*, const cuuint64_t*, const cuuint64_t*, const cuuint32_t*,
                             const cuuint32_t*, CUtensorMapInterleave, CUtensorMapSwizzle, CUtensorMapL2promotion, CUtensorMapFloatOOBfill);

struct Dim { cuuint64_t n, stride; cuuint32_t box; };
template <int RANK>
void make_map(EncodeFn enc, CUtensorMap* m, bool words, int swz, const void* ptr, const Dim (&d)[RANK]) {
  cuuint64_t gd[RANK], gs[RANK];
  cuuint32_t bx[RANK], es[RANK];
  for (int i = 0; i < RANK; i++) { gd[i] = d[i].n; gs[i] = d[i].stride; bx[i] = d[i].box; es[i] = 1; }
  enc(m, words ? CU_TENSOR_MAP_DATA_TYPE_UINT32 : CU_TENSOR_MAP_DATA_TYPE_BFLOAT16, RANK, const_cast<void*>(ptr), gd, gs + 1, bx, es,
      CU_TENSOR_MAP_INTERLEAVE_NONE, static_cast<CUtensorMapSwizzle>(swz),
      swz == 3 ? CU_TENSOR_MAP_L2_PROMOTION_L2_256B : CU_TENSOR_MAP_L2_PROMOTION_NONE, CU_TENSOR_MAP_FLOAT_OOB_FILL_NONE);
}

}

extern "C" void kernel_launch(void* const* d_in, const int* in_sizes, int n_in, void* d_out, int out_size) {
  (void)in_sizes; (void)n_in; (void)out_size;
  static EncodeFn enc = nullptr;
  static void *sptr = nullptr, *tptr = nullptr;
  if (!enc) {
    void* f = nullptr; cudaDriverEntryPointQueryResult qr;
    cudaGetDriverEntryPoint("cuTensorMapEncodeTiled", &f, cudaEnableDefault, &qr);
    enc = reinterpret_cast<EncodeFn>(f);
    cudaFuncSetAttribute(fused_kernel, cudaFuncAttributeMaxDynamicSharedMemorySize, SMEM_BYTES);
    cudaGetSymbolAddress(&sptr, g_s);
    cudaGetSymbolAddress(&tptr, T_TAB);
  }
  Params p;
  p.x = (const __nv_bfloat16*)d_in[0]; p.wr = (const __nv_bfloat16*)d_in[1]; p.wi = (const __nv_bfloat16*)d_in[2];
  p.b1 = (const __nv_bfloat16*)d_in[5]; p.b2 = (const __nv_bfloat16*)d_in[7];
  p.c = (const __nv_bfloat16*)d_in[8]; p.wmod = (const __nv_bfloat16*)d_in[9];
  p.w1 = (const __nv_bfloat16*)d_in[4]; p.w2 = (const __nv_bfloat16*)d_in[6];
  p.out = static_cast<uint32_t*>(d_out); p.s = static_cast<Scratch*>(sptr); p.tab = static_cast<const uint4*>(tptr);
  Maps maps;
  make_map<4>(enc, &maps.w1a, false, 3, p.w1, {{64, 0, 64}, {16, 128 * 2 * F_, 4}, {128, 2 * F_, 16}, {72, 128, 2}});
  make_map<4>(enc, &maps.w1b, false, 3, p.w1, {{64, 0, 64}, {16, 128 * 2 * F_, 4}, {128, 2 * F_, 16}, {72, 128, 3}});
  make_map<3>(enc, &maps.w2, false, 3, p.w2, {{64, 0, 64}, {F_, 2 * S_, 64}, {32, 128, 2}});
  make_map<2>(enc, &maps.z1, true, 0, p.s->z1, {{5120, 0, 40}, {120, 20480, 60}});
  for (int i = 0; i < 2; i++) make_map<2>(enc, &maps.z2[i], true, 0, p.s->z2, {{4800, 0, i ? 16u : 24u}, {128, 19200, 128}});
  for (int i = 0; i < 4; i++) make_map<2>(enc, &maps.wf[i], false, 2 - (i & 1), (i & 2) ? p.wi : p.wr, {{16 * DF_, 0, (i & 1) ? 16u : 32u}, {128, 32 * DF_, 128}});
  make_map<2>(enc, &maps.wm, false, 1, p.wmod, {{6 * D_, 0, 16}, {D_, 12 * D_, 192}});
  make_map<3>(enc, &maps.h3, true, 0, p.s->h3, {{1024, 0, 64}, {144, 4096, 18}, {4, 144 * 4096, 3}});
  fused_kernel<<<NCTA, NTHR, SMEM_BYTES, cudaStreamPerThread>>>(p, maps);
}
```

```cpp
#include <cuda_runtime.h>
#include <cuda_bf16.h>
#include <cuda.h>
#include <stdint.h>

namespace {

constexpr int S_ = 2048, D_ = 576, DF_ = 289, F_ = 4608;
constexpr int NCTA = 132, NTHR = 384;
constexpr int STAGE = 36864, NST = 6;
constexpr int STAGE2 = 34816, O_U1 = NST * STAGE2, O_GB = O_U1 + 20480, SMEM_BYTES = 232448;
constexpr uint32_t sbase = 1024, red = sbase + NST * STAGE, full0 = sbase + SMEM_BYTES - 256, empty0 = full0 + 8 * NST;
constexpr int O_NRM = 0, O_B1 = 19456, O_Z1 = 38912, O_P2 = 59392, O_ST = 3 * STAGE;
constexpr int O_RAW = 4 * STAGE;
constexpr int O_IN = 4 * STAGE, O_Y = O_IN + 19456, O_B3 = O_IN + 38912, O_MOD = O_IN + 57344;

__device__ __align__(128) const uint32_t T_TAB[5632] = {
0x3f803f80,0xbf803f80,0x3f803f80,0xbf803f80,0x3f803f80,0xbf803f80,0x3f803f80,0xbf803f80,0x3f803f80,0xbf803f80,0x3f803f80,0xbf803f80,
0x3f803f80,0xbf803f80,0x3f803f80,0xbf803f80,0x3f7f3f80,0xbdc90000,0x3f223f35,0xbf46bf35,0x3f753f7b,0xbe95be48,0x3ef13f0e,0xbf62bf55,
0x3f623f6d,0xbef1bec4,0x3e953ec4,0xbf75bf6d,0x3f463f55,0xbf22bf0e,0x3dc93e48,0xbf7fbf7b,0x3f7b3f80,0xbe480000,0xbe480000,0xbf7bbf80,
0x3f553f6d,0xbf0ebec4,0xbf0ebec4,0xbf55bf6d,0x3f0e3f35,0xbf55bf35,0xbf55bf35,0xbf0ebf35,0x3e483ec4,0xbf7bbf6d,0xbf7bbf6d,0xbe48bec4,
0x3f753f80,0xbe950000,0xbf62bf35,0xbef1bf35,0x3f223f55,0xbf46bf0e,0xbf7fbf7b,0x3dc9be48,0x3dc93ec4,0xbf7fbf6d,0xbf46bf6d,0x3f223ec4,
0xbef1be48,0xbf62bf7b,0xbe95bf0e,0x3f753f55,0x3f6d3f80,0xbec40000,0xbf6dbf80,0x3ec40000,0x3ec43f35,0xbf6dbf35,0xbec4bf35,0x3f6d3f35,
0xbec40000,0xbf6dbf80,0x3ec40000,0x3f6d3f80,0xbf6dbf35,0xbec4bf35,0x3f6d3f35,0x3ec43f35,0x3f623f80,0xbef10000,0xbe95bf35,0x3f753f35,
0x3dc93f0e,0xbf7fbf55,0x3f223e48,0x3f463f7b,0xbf46bec4,0xbf22bf6d,0x3f7f3f6d,0xbdc93ec4,0xbf75bf7b,0x3e95be48,0x3ef13f55,0xbf62bf0e,
0x3f553f80,0xbf0e0000,0x3f0e0000,0x3f553f80,0xbe483ec4,0xbf7bbf6d,0x3f7b3f6d,0xbe483ec4,0xbf7bbf35,0xbe48bf35,0x3e483f35,0xbf7bbf35,
0xbf0ebf6d,0x3f553ec4,0xbf55bec4,0xbf0ebf6d,0x3f463f80,0xbf220000,0x3f7f3f35,0x3dc93f35,0xbef13e48,0xbf62bf7b,0x3e953f55,0xbf75bf0e,
0xbf75bf6d,0x3e95bec4,0xbf62bec4,0xbef1bf6d,0x3dc9bf0e,0x3f7f3f55,0xbf22bf7b,0x3f463e48,0x3f353f80,0xbf350000,0x3f353f80,0xbf350000,
0xbf350000,0xbf35bf80,0xbf350000,0xbf35bf80,0xbf35bf80,0x3f350000,0xbf35bf80,0x3f350000,0x3f350000,0x3f353f80,0x3f350000,0x3f353f80,
0x3f223f80,0xbf460000,0xbdc93f35,0xbf7fbf35,0xbf62be48,0xbef1bf7b,0xbf75bf55,0x3e95bf0e,0xbe95bf6d,0x3f753ec4,0x3ef1bec4,0x3f623f6d,
0x3f7f3f0e,0x3dc93f55,0x3f463f7b,0xbf223e48,0x3f0e3f80,0xbf550000,0xbf550000,0xbf0ebf80,0xbf7bbec4,0xbe48bf6d,0xbe48bf6d,0x3f7b3ec4,
0x3e48bf35,0x3f7b3f35,0x3f7b3f35,0xbe483f35,0x3f553f6d,0xbf0e3ec4,0xbf0e3ec4,0xbf55bf6d,0x3ef13f80,0xbf620000,0xbf75bf35,0x3e95bf35,
0xbf7fbf0e,0x3dc9bf55,0x3f46be48,0x3f223f7b,0x3f22bec4,0x3f463f6d,0x3dc93f6d,0xbf7fbec4,0x3e953f7b,0xbf75be48,0xbf62bf55,0x3ef1bf0e,
0x3ec43f80,0xbf6d0000,0xbec4bf80,0x3f6d0000,0xbf6dbf35,0x3ec4bf35,0x3f6d3f35,0xbec43f35,0x3f6d0000,0x3ec43f80,0xbf6d0000,0xbec4bf80,
0xbec43f35,0xbf6dbf35,0x3ec4bf35,0x3f6d3f35,0x3e953f80,0xbf750000,0x3ef1bf35,0x3f623f35,0xbf46bf55,0x3f22bf0e,0x3dc93f7b,0xbf7fbe48,
0x3f7f3ec4,0xbdc93f6d,0xbf22bf6d,0x3f46bec4,0xbf623e48,0xbef1bf7b,0x3f753f0e,0xbe953f55,0x3e483f80,0xbf7b0000,0x3f7b0000,0x3e483f80,
0xbf0ebf6d,0x3f55bec4,0xbf553ec4,0xbf0ebf6d,0x3f553f35,0xbf0e3f35,0x3f0ebf35,0x3f553f35,0xbf7bbec4,0x3e48bf6d,0xbe483f6d,0xbf7bbec4,
0x3dc93f80,0xbf7f0000,0x3f463f35,0xbf223f35,0xbe95bf7b,0x3f75be48,0xbf62bf0e,0x3ef1bf55,0x3ef13f6d,0xbf623ec4,0x3f753ec4,0xbe953f6d,
0xbf22bf55,0x3f46bf0e,0xbf7fbe48,0x3dc9bf7b,0x3f80,0xbf800000,0x3f80,0xbf800000,0xbf80,0x3f800000,0xbf80,0x3f800000,
0x3f80,0xbf800000,0x3f80,0xbf800000,0xbf80,0x3f800000,0xbf80,0x3f800000,0xbdc93f80,0xbf7f0000,0xbf463f35,0xbf22bf35,
0x3e95bf7b,0x3f753e48,0x3f62bf0e,0x3ef13f55,0xbef13f6d,0xbf62bec4,0xbf753ec4,0xbe95bf6d,0x3f22bf55,0x3f463f0e,0x3f7fbe48,0x3dc93f7b,
0xbe483f80,0xbf7b0000,0xbf7b0000,0x3e48bf80,0x3f0ebf6d,0x3f553ec4,0x3f553ec4,0xbf0e3f6d,0xbf553f35,0xbf0ebf35,0xbf0ebf35,0x3f55bf35,
0x3f7bbec4,0x3e483f6d,0x3e483f6d,0xbf7b3ec4,0xbe953f80,0xbf750000,0xbef1bf35,0x3f62bf35,0x3f46bf55,0x3f223f0e,0xbdc93f7b,0xbf7f3e48,
0xbf7f3ec4,0xbdc9bf6d,0x3f22bf6d,0x3f463ec4,0x3f623e48,0xbef13f7b,0xbf753f0e,0xbe95bf55,0xbec43f80,0xbf6d0000,0x3ec4bf80,0x3f6d0000,
0x3f6dbf35,0x3ec43f35,0xbf6d3f35,0xbec4bf35,0xbf6d0000,0x3ec4bf80,0x3f6d0000,0xbec43f80,0x3ec43f35,0xbf6d3f35,0xbec4bf35,0x3f6dbf35,
0xbef13f80,0xbf620000,0x3f75bf35,0x3e953f35,0x3f7fbf0e,0x3dc93f55,0xbf46be48,0x3f22bf7b,0xbf22bec4,0x3f46bf6d,0xbdc93f6d,0xbf7f3ec4,
0xbe953f7b,0xbf753e48,0x3f62bf55,0x3ef13f0e,0xbf0e3f80,0xbf550000,0x3f550000,0xbf0e3f80,0x3f7bbec4,0xbe483f6d,0x3e48bf6d,0x3f7bbec4,
0xbe48bf35,0x3f7bbf35,0xbf7b3f35,0xbe48bf35,0xbf553f6d,0xbf0ebec4,0x3f0e3ec4,0xbf553f6d,0xbf223f80,0xbf460000,0x3dc93f35,0xbf7f3f35,
0x3f62be48,0xbef13f7b,0x3f75bf55,0x3e953f0e,0x3e95bf6d,0x3f75bec4,0xbef1bec4,0x3f62bf6d,0xbf7f3f0e,0x3dc9bf55,0xbf463f7b,0xbf22be48,
0xbf353f80,0xbf350000,0xbf353f80,0xbf350000,0x3f350000,0xbf353f80,0x3f350000,0xbf353f80,0x3f35bf80,0x3f350000,0x3f35bf80,0x3f350000,
0xbf350000,0x3f35bf80,0xbf350000,0x3f35bf80,0xbf463f80,0xbf220000,0xbf7f3f35,0x3dc9bf35,0x3ef13e48,0xbf623f7b,0xbe953f55,0xbf753f0e,
0x3f75bf6d,0x3e953ec4,0x3f62bec4,0xbef13f6d,0xbdc9bf0e,0x3f7fbf55,0x3f22bf7b,0x3f46be48,0xbf553f80,0xbf0e0000,0xbf0e0000,0x3f55bf80,
0x3e483ec4,0xbf7b3f6d,0xbf7b3f6d,0xbe48bec4,0x3f7bbf35,0xbe483f35,0xbe483f35,0xbf7b3f35,0x3f0ebf6d,0x3f55bec4,0x3f55bec4,0xbf0e3f6d,
0xbf623f80,0xbef10000,0x3e95bf35,0x3f75bf35,0xbdc93f0e,0xbf7f3f55,0xbf223e48,0x3f46bf7b,0x3f46bec4,0xbf223f6d,0xbf7f3f6d,0xbdc9bec4,
0x3f75bf7b,0x3e953e48,0xbef13f55,0xbf623f0e,0xbf6d3f80,0xbec40000,0x3f6dbf80,0x3ec40000,0xbec43f35,0xbf6d3f35,0x3ec4bf35,0x3f6dbf35,
0x3ec40000,0xbf6d3f80,0xbec40000,0x3f6dbf80,0x3f6dbf35,0xbec43f35,0xbf6d3f35,0x3ec4bf35,0xbf753f80,0xbe950000,0x3f62bf35,0xbef13f35,
0xbf223f55,0xbf463f0e,0x3f7fbf7b,0x3dc93e48,0xbdc93ec4,0xbf7f3f6d,0x3f46bf6d,0x3f22bec4,0x3ef1be48,0xbf623f7b,0x3e95bf0e,0x3f75bf55,
0xbf7b3f80,0xbe480000,0x3e480000,0xbf7b3f80,0xbf553f6d,0xbf0e3ec4,0x3f0ebec4,0xbf553f6d,0xbf0e3f35,0xbf553f35,0x3f55bf35,0xbf0e3f35,
0xbe483ec4,0xbf7b3f6d,0x3f7bbf6d,0xbe483ec4,0xbf7f3f80,0xbdc90000,0xbf223f35,0xbf463f35,0xbf753f7b,0xbe953e48,0xbef13f0e,0xbf623f55,
0xbf623f6d,0xbef13ec4,0xbe953ec4,0xbf753f6d,0xbf463f55,0xbf223f0e,0xbdc93e48,0xbf7f3f7b,0x3f803f80,0xbf803f80,0x3f803f80,0xbf803f80,
0x3f803f80,0xbf803f80,0x3f803f80,0xbf803f80,0x3f803f80,0xbf803f80,0x3f803f80,0xbf803f80,0x3f803f80,0xbf803f80,0x3f803f80,0xbf803f80,
0xbdc90000,0xbf7fbf80,0xbf46bf35,0xbf22bf35,0xbe95be48,0xbf75bf7b,0xbf62bf55,0xbef1bf0e,0xbef1bec4,0xbf62bf6d,0xbf75bf6d,0xbe95bec4,
0xbf22bf0e,0xbf46bf55,0xbf7fbf7b,0xbdc9be48,0xbf7bbf80,0x3e480000,0x3e480000,0x3f7b3f80,0xbf55bf6d,0x3f0e3ec4,0x3f0e3ec4,0x3f553f6d,
0xbf0ebf35,0x3f553f35,0x3f553f35,0x3f0e3f35,0xbe48bec4,0x3f7b3f6d,0x3f7b3f6d,0x3e483ec4,0x3e950000,0x3f753f80,0x3ef13f35,0xbf62bf35,
0x3f463f0e,0x3f223f55,0xbdc93e48,0xbf7fbf7b,0x3f7f3f6d,0x3dc93ec4,0xbf22bec4,0xbf46bf6d,0x3f623f7b,0xbef1be48,0xbf75bf55,0xbe95bf0e,
0x3f6d3f80,0xbec40000,0xbf6dbf80,0x3ec40000,0x3ec43f35,0xbf6dbf35,0xbec4bf35,0x3f6d3f35,0xbec40000,0xbf6dbf80,0x3ec40000,0x3f6d3f80,
0xbf6dbf35,0xbec4bf35,0x3f6d3f35,0x3ec43f35,0xbef10000,0xbf62bf80,0x3f753f35,0x3e953f35,0xbf7fbf55,0xbdc9bf0e,0x3f463f7b,0xbf22be48,
0xbf22bf6d,0x3f463ec4,0xbdc93ec4,0xbf7fbf6d,0x3e95be48,0x3f753f7b,0xbf62bf0e,0xbef1bf55,0xbf55bf80,0x3f0e0000,0xbf0e0000,0xbf55bf80,
0x3e48bec4,0x3f7b3f6d,0xbf7bbf6d,0x3e48bec4,0x3f7b3f35,0x3e483f35,0xbe48bf35,0x3f7b3f35,0x3f0e3f6d,0xbf55bec4,0x3f553ec4,0x3f0e3f6d,
0x3f220000,0x3f463f80,0xbdc9bf35,0x3f7f3f35,0x3f623f7b,0xbef13e48,0x3f753f0e,0x3e953f55,0xbe953ec4,0xbf75bf6d,0x3ef13f6d,0xbf62bec4,
0xbf7fbf55,0x3dc9bf0e,0xbf46be48,0xbf22bf7b,0x3f353f80,0xbf350000,0x3f353f80,0xbf350000,0xbf350000,0xbf35bf80,0xbf350000,0xbf35bf80,
0xbf35bf80,0x3f350000,0xbf35bf80,0x3f350000,0x3f350000,0x3f353f80,0x3f350000,0x3f353f80,0xbf460000,0xbf22bf80,0xbf7fbf35,0x3dc9bf35,
0xbef1bf7b,0x3f623e48,0x3e95bf0e,0x3f753f55,0x3f753ec4,0x3e953f6d,0x3f623f6d,0xbef13ec4,0x3dc93f55,0xbf7fbf0e,0xbf223e48,0xbf46bf7b,
0xbf0ebf80,0x3f550000,0x3f550000,0x3f0e3f80,0x3f7b3ec4,0x3e483f6d,0x3e483f6d,0xbf7bbec4,0xbe483f35,0xbf7bbf35,0xbf7bbf35,0x3e48bf35,
0xbf55bf6d,0x3f0ebec4,0x3f0ebec4,0x3f553f6d,0x3f620000,0x3ef13f80,0xbe953f35,0xbf75bf35,0xbdc93f55,0xbf7fbf0e,0xbf22bf7b,0x3f46be48,
0xbf46bf6d,0x3f22bec4,0x3f7f3ec4,0x3dc93f6d,0x3f753e48,0x3e953f7b,0xbef13f0e,0xbf62bf55,0x3ec43f80,0xbf6d0000,0xbec4bf80,0x3f6d0000,
0xbf6dbf35,0x3ec4bf35,0x3f6d3f35,0xbec43f35,0x3f6d0000,0x3ec43f80,0xbf6d0000,0xbec4bf80,0xbec43f35,0xbf6dbf35,0x3ec4bf35,0x3f6d3f35,
0xbf750000,0xbe95bf80,0x3f623f35,0xbef13f35,0x3f22bf0e,0x3f463f55,0xbf7fbe48,0xbdc9bf7b,0xbdc93f6d,0xbf7fbec4,0x3f46bec4,0x3f223f6d,
0xbef1bf7b,0x3f62be48,0xbe953f55,0xbf75bf0e,0xbe48bf80,0x3f7b0000,0xbf7b0000,0xbe48bf80,0x3f0e3f6d,0xbf553ec4,0x3f55bec4,0x3f0e3f6d,
0xbf55bf35,0x3f0ebf35,0xbf0e3f35,0xbf55bf35,0x3f7b3ec4,0xbe483f6d,0x3e48bf6d,0x3f7b3ec4,0x3f7f0000,0x3dc93f80,0x3f22bf35,0x3f463f35,
0xbf753e48,0xbe95bf7b,0xbef13f55,0xbf62bf0e,0x3f62bec4,0x3ef13f6d,0x3e95bf6d,0x3f753ec4,0xbf463f0e,0xbf22bf55,0xbdc93f7b,0xbf7fbe48,
0x3f80,0xbf800000,0x3f80,0xbf800000,0xbf80,0x3f800000,0xbf80,0x3f800000,0x3f80,0xbf800000,0x3f80,0xbf800000,
0xbf80,0x3f800000,0xbf80,0x3f800000,0xbf7f0000,0x3dc9bf80,0xbf22bf35,0x3f46bf35,0x3f753e48,0xbe953f7b,0x3ef13f55,0xbf623f0e,
0xbf62bec4,0x3ef1bf6d,0xbe95bf6d,0x3f75bec4,0x3f463f0e,0xbf223f55,0x3dc93f7b,0xbf7f3e48,0x3e48bf80,0x3f7b0000,0x3f7b0000,0xbe483f80,
0xbf0e3f6d,0xbf55bec4,0xbf55bec4,0x3f0ebf6d,0x3f55bf35,0x3f0e3f35,0x3f0e3f35,0xbf553f35,0xbf7b3ec4,0xbe48bf6d,0xbe48bf6d,0x3f7bbec4,
0x3f750000,0xbe953f80,0xbf623f35,0xbef1bf35,0xbf22bf0e,0x3f46bf55,0x3f7fbe48,0xbdc93f7b,0x3dc93f6d,0xbf7f3ec4,0xbf46bec4,0x3f22bf6d,
0x3ef1bf7b,0x3f623e48,0x3e953f55,0xbf753f0e,0xbec43f80,0xbf6d0000,0x3ec4bf80,0x3f6d0000,0x3f6dbf35,0x3ec43f35,0xbf6d3f35,0xbec4bf35,
0xbf6d0000,0x3ec4bf80,0x3f6d0000,0xbec43f80,0x3ec43f35,0xbf6d3f35,0xbec4bf35,0x3f6dbf35,0xbf620000,0x3ef1bf80,0x3e953f35,0xbf753f35,
0x3dc93f55,0xbf7f3f0e,0x3f22bf7b,0x3f463e48,0x3f46bf6d,0x3f223ec4,0xbf7f3ec4,0x3dc9bf6d,0xbf753e48,0x3e95bf7b,0x3ef13f0e,0xbf623f55,
0x3f0ebf80,0x3f550000,0xbf550000,0x3f0ebf80,0xbf7b3ec4,0x3e48bf6d,0xbe483f6d,0xbf7b3ec4,0x3e483f35,0xbf7b3f35,0x3f7bbf35,0x3e483f35,
0x3f55bf6d,0x3f0e3ec4,0xbf0ebec4,0x3f55bf6d,0x3f460000,0xbf223f80,0x3f7fbf35,0x3dc93f35,0x3ef1bf7b,0x3f62be48,0xbe95bf0e,0x3f75bf55,
0xbf753ec4,0x3e95bf6d,0xbf623f6d,0xbef1bec4,0xbdc93f55,0xbf7f3f0e,0x3f223e48,0xbf463f7b,0xbf353f80,0xbf350000,0xbf353f80,0xbf350000,
0x3f350000,0xbf353f80,0x3f350000,0xbf353f80,0x3f35bf80,0x3f350000,0x3f35bf80,0x3f350000,0xbf350000,0x3f35bf80,0xbf350000,0x3f35bf80,
0xbf220000,0x3f46bf80,0x3dc9bf35,0x3f7fbf35,0xbf623f7b,0xbef1be48,0xbf753f0e,0x3e95bf55,0x3e953ec4,0xbf753f6d,0xbef13f6d,0xbf623ec4,
0x3f7fbf55,0x3dc93f0e,0x3f46be48,0xbf223f7b,0x3f55bf80,0x3f0e0000,0x3f0e0000,0xbf553f80,0xbe48bec4,0x3f7bbf6d,0x3f7bbf6d,0x3e483ec4,
0xbf7b3f35,0x3e48bf35,0x3e48bf35,0x3f7bbf35,0xbf0e3f6d,0xbf553ec4,0xbf553ec4,0x3f0ebf6d,0x3ef10000,0xbf623f80,0xbf753f35,0x3e95bf35,
0x3f7fbf55,0xbdc93f0e,0xbf463f7b,0xbf223e48,0x3f22bf6d,0x3f46bec4,0x3dc93ec4,0xbf7f3f6d,0xbe95be48,0x3f75bf7b,0x3f62bf0e,0xbef13f55,
0xbf6d3f80,0xbec40000,0x3f6dbf80,0x3ec40000,0xbec43f35,0xbf6d3f35,0x3ec4bf35,0x3f6dbf35,0x3ec40000,0xbf6d3f80,0xbec40000,0x3f6dbf80,
0x3f6dbf35,0xbec43f35,0xbf6d3f35,0x3ec4bf35,0xbe950000,0x3f75bf80,0xbef13f35,0xbf623f35,0xbf463f0e,0x3f22bf55,0x3dc93e48,0xbf7f3f7b,
0xbf7f3f6d,0x3dc9bec4,0x3f22bec4,0xbf463f6d,0xbf623f7b,0xbef13e48,0x3f75bf55,0xbe953f0e,0x3f7bbf80,0x3e480000,0xbe480000,0x3f7bbf80,
0x3f55bf6d,0x3f0ebec4,0xbf0e3ec4,0x3f55bf6d,0x3f0ebf35,0x3f55bf35,0xbf553f35,0x3f0ebf35,0x3e48bec4,0x3f7bbf6d,0xbf7b3f6d,0x3e48bec4,
0x3dc90000,0xbf7f3f80,0x3f46bf35,0xbf223f35,0x3e95be48,0xbf753f7b,0x3f62bf55,0xbef13f0e,0x3ef1bec4,0xbf623f6d,0x3f75bf6d,0xbe953ec4,
0x3f22bf0e,0xbf463f55,0x3f7fbf7b,0xbdc93e48,0x3f803f80,0xbf803f80,0x3f803f80,0xbf803f80,0x3f803f80,0xbf803f80,0x3f803f80,0xbf803f80,
0x3f803f80,0xbf803f80,0x3f803f80,0xbf803f80,0x3f803f80,0xbf803f80,0x3f803f80,0xbf803f80,0xbf7fbf80,0x3dc90000,0xbf22bf35,0x3f463f35,
0xbf75bf7b,0x3e953e48,0xbef1bf0e,0x3f623f55,0xbf62bf6d,0x3ef13ec4,0xbe95bec4,0x3f753f6d,0xbf46bf55,0x3f223f0e,0xbdc9be48,0x3f7f3f7b,
0x3f7b3f80,0xbe480000,0xbe480000,0xbf7bbf80,0x3f553f6d,0xbf0ebec4,0xbf0ebec4,0xbf55bf6d,0x3f0e3f35,0xbf55bf35,0xbf55bf35,0xbf0ebf35,
0x3e483ec4,0xbf7bbf6d,0xbf7bbf6d,0xbe48bec4,0xbf75bf80,0x3e950000,0x3f623f35,0x3ef13f35,0xbf22bf55,0x3f463f0e,0x3f7f3f7b,0xbdc93e48,
0xbdc9bec4,0x3f7f3f6d,0x3f463f6d,0xbf22bec4,0x3ef13e48,0x3f623f7b,0x3e953f0e,0xbf75bf55,0x3f6d3f80,0xbec40000,0xbf6dbf80,0x3ec40000,
0x3ec43f35,0xbf6dbf35,0xbec4bf35,0x3f6d3f35,0xbec40000,0xbf6dbf80,0x3ec40000,0x3f6d3f80,0xbf6dbf35,0xbec4bf35,0x3f6d3f35,0x3ec43f35,
0xbf62bf80,0x3ef10000,0x3e953f35,0xbf75bf35,0xbdc9bf0e,0x3f7f3f55,0xbf22be48,0xbf46bf7b,0x3f463ec4,0x3f223f6d,0xbf7fbf6d,0x3dc9bec4,
0x3f753f7b,0xbe953e48,0xbef1bf55,0x3f623f0e,0x3f553f80,0xbf0e0000,0x3f0e0000,0x3f553f80,0xbe483ec4,0xbf7bbf6d,0x3f7b3f6d,0xbe483ec4,
0xbf7bbf35,0xbe48bf35,0x3e483f35,0xbf7bbf35,0xbf0ebf6d,0x3f553ec4,0xbf55bec4,0xbf0ebf6d,0xbf46bf80,0x3f220000,0xbf7fbf35,0xbdc9bf35,
0x3ef1be48,0x3f623f7b,0xbe95bf55,0x3f753f0e,0x3f753f6d,0xbe953ec4,0x3f623ec4,0x3ef13f6d,0xbdc93f0e,0xbf7fbf55,0x3f223f7b,0xbf46be48,
0x3f353f80,0xbf350000,0x3f353f80,0xbf350000,0xbf350000,0xbf35bf80,0xbf350000,0xbf35bf80,0xbf35bf80,0x3f350000,0xbf35bf80,0x3f350000,
0x3f350000,0x3f353f80,0x3f350000,0x3f353f80,0xbf22bf80,0x3f460000,0x3dc9bf35,0x3f7f3f35,0x3f623e48,0x3ef13f7b,0x3f753f55,0xbe953f0e,
0x3e953f6d,0xbf75bec4,0xbef13ec4,0xbf62bf6d,0xbf7fbf0e,0xbdc9bf55,0xbf46bf7b,0x3f22be48,0x3f0e3f80,0xbf550000,0xbf550000,0xbf0ebf80,
0xbf7bbec4,0xbe48bf6d,0xbe48bf6d,0x3f7b3ec4,0x3e48bf35,0x3f7b3f35,0x3f7b3f35,0xbe483f35,0x3f553f6d,0xbf0e3ec4,0xbf0e3ec4,0xbf55bf6d,
0xbef1bf80,0x3f620000,0x3f753f35,0xbe953f35,0x3f7f3f0e,0xbdc93f55,0xbf463e48,0xbf22bf7b,0xbf223ec4,0xbf46bf6d,0xbdc9bf6d,0x3f7f3ec4,
0xbe95bf7b,0x3f753e48,0x3f623f55,0xbef13f0e,0x3ec43f80,0xbf6d0000,0xbec4bf80,0x3f6d0000,0xbf6dbf35,0x3ec4bf35,0x3f6d3f35,0xbec43f35,
0x3f6d0000,0x3ec43f80,0xbf6d0000,0xbec4bf80,0xbec43f35,0xbf6dbf35,0x3ec4bf35,0x3f6d3f35,0xbe95bf80,0x3f750000,0xbef13f35,0xbf62bf35,
0x3f463f55,0xbf223f0e,0xbdc9bf7b,0x3f7f3e48,0xbf7fbec4,0x3dc9bf6d,0x3f223f6d,0xbf463ec4,0x3f62be48,0x3ef13f7b,0xbf75bf0e,0x3e95bf55,
0x3e483f80,0xbf7b0000,0x3f7b0000,0x3e483f80,0xbf0ebf6d,0x3f55bec4,0xbf553ec4,0xbf0ebf6d,0x3f553f35,0xbf0e3f35,0x3f0ebf35,0x3f553f35,
0xbf7bbec4,0x3e48bf6d,0xbe483f6d,0xbf7bbec4,0xbdc9bf80,0x3f7f0000,0xbf46bf35,0x3f22bf35,0x3e953f7b,0xbf753e48,0x3f623f0e,0xbef13f55,
0xbef1bf6d,0x3f62bec4,0xbf75bec4,0x3e95bf6d,0x3f223f55,0xbf463f0e,0x3f7f3e48,0xbdc93f7b,0x3f80,0xbf800000,0x3f80,0xbf800000,
0xbf80,0x3f800000,0xbf80,0x3f800000,0x3f80,0xbf800000,0x3f80,0xbf800000,0xbf80,0x3f800000,0xbf80,0x3f800000,
0x3dc9bf80,0x3f7f0000,0x3f46bf35,0x3f223f35,0xbe953f7b,0xbf75be48,0xbf623f0e,0xbef1bf55,0x3ef1bf6d,0x3f623ec4,0x3f75bec4,0x3e953f6d,
0xbf223f55,0xbf46bf0e,0xbf7f3e48,0xbdc9bf7b,0xbe483f80,0xbf7b0000,0xbf7b0000,0x3e48bf80,0x3f0ebf6d,0x3f553ec4,0x3f553ec4,0xbf0e3f6d,
0xbf553f35,0xbf0ebf35,0xbf0ebf35,0x3f55bf35,0x3f7bbec4,0x3e483f6d,0x3e483f6d,0xbf7b3ec4,0x3e95bf80,0x3f750000,0x3ef13f35,0xbf623f35,
0xbf463f55,0xbf22bf0e,0x3dc9bf7b,0x3f7fbe48,0x3f7fbec4,0x3dc93f6d,0xbf223f6d,0xbf46bec4,0xbf62be48,0x3ef1bf7b,0x3f75bf0e,0x3e953f55,
0xbec43f80,0xbf6d0000,0x3ec4bf80,0x3f6d0000,0x3f6dbf35,0x3ec43f35,0xbf6d3f35,0xbec4bf35,0xbf6d0000,0x3ec4bf80,0x3f6d0000,0xbec43f80,
0x3ec43f35,0xbf6d3f35,0xbec4bf35,0x3f6dbf35,0x3ef1bf80,0x3f620000,0xbf753f35,0xbe95bf35,0xbf7f3f0e,0xbdc9bf55,0x3f463e48,0xbf223f7b,
0x3f223ec4,0xbf463f6d,0x3dc9bf6d,0x3f7fbec4,0x3e95bf7b,0x3f75be48,0xbf623f55,0xbef1bf0e,0xbf0e3f80,0xbf550000,0x3f550000,0xbf0e3f80,
0x3f7bbec4,0xbe483f6d,0x3e48bf6d,0x3f7bbec4,0xbe48bf35,0x3f7bbf35,0xbf7b3f35,0xbe48bf35,0xbf553f6d,0xbf0ebec4,0x3f0e3ec4,0xbf553f6d,
0x3f22bf80,0x3f460000,0xbdc9bf35,0x3f7fbf35,0xbf623e48,0x3ef1bf7b,0xbf753f55,0xbe95bf0e,0xbe953f6d,0xbf753ec4,0x3ef13ec4,0xbf623f6d,
0x3f7fbf0e,0xbdc93f55,0x3f46bf7b,0x3f223e48,0xbf353f80,0xbf350000,0xbf353f80,0xbf350000,0x3f350000,0xbf353f80,0x3f350000,0xbf353f80,
0x3f35bf80,0x3f350000,0x3f35bf80,0x3f350000,0xbf350000,0x3f35bf80,0xbf350000,0x3f35bf80,0x3f46bf80,0x3f220000,0x3f7fbf35,0xbdc93f35,
0xbef1be48,0x3f62bf7b,0x3e95bf55,0x3f75bf0e,0xbf753f6d,0xbe95bec4,0xbf623ec4,0x3ef1bf6d,0x3dc93f0e,0xbf7f3f55,0xbf223f7b,0xbf463e48,
0xbf553f80,0xbf0e0000,0xbf0e0000,0x3f55bf80,0x3e483ec4,0xbf7b3f6d,0xbf7b3f6d,0xbe48bec4,0x3f7bbf35,0xbe483f35,0xbe483f35,0xbf7b3f35,
0x3f0ebf6d,0x3f55bec4,0x3f55bec4,0xbf0e3f6d,0x3f62bf80,0x3ef10000,0xbe953f35,0xbf753f35,0x3dc9bf0e,0x3f7fbf55,0x3f22be48,0xbf463f7b,
0xbf463ec4,0x3f22bf6d,0x3f7fbf6d,0x3dc93ec4,0xbf753f7b,0xbe95be48,0x3ef1bf55,0x3f62bf0e,0xbf6d3f80,0xbec40000,0x3f6dbf80,0x3ec40000,
0xbec43f35,0xbf6d3f35,0x3ec4bf35,0x3f6dbf35,0x3ec40000,0xbf6d3f80,0xbec40000,0x3f6dbf80,0x3f6dbf35,0xbec43f35,0xbf6d3f35,0x3ec4bf35,
0x3f75bf80,0x3e950000,0xbf623f35,0x3ef1bf35,0x3f22bf55,0x3f46bf0e,0xbf7f3f7b,0xbdc9be48,0x3dc9bec4,0x3f7fbf6d,0xbf463f6d,0xbf223ec4,
0xbef13e48,0x3f62bf7b,0xbe953f0e,0xbf753f55,0xbf7b3f80,0xbe480000,0x3e480000,0xbf7b3f80,0xbf553f6d,0xbf0e3ec4,0x3f0ebec4,0xbf553f6d,
0xbf0e3f35,0xbf553f35,0x3f55bf35,0xbf0e3f35,0xbe483ec4,0xbf7b3f6d,0x3f7bbf6d,0xbe483ec4,0x3f7fbf80,0x3dc90000,0x3f22bf35,0x3f46bf35,
0x3f75bf7b,0x3e95be48,0x3ef1bf0e,0x3f62bf55,0x3f62bf6d,0x3ef1bec4,0x3e95bec4,0x3f75bf6d,0x3f46bf55,0x3f22bf0e,0x3dc9be48,0x3f7fbf7b,
0x3f803f80,0xbf803f80,0x3f803f80,0xbf803f80,0x3f803f80,0xbf803f80,0x3f803f80,0xbf803f80,0x3f803f80,0xbf803f80,0x3f803f80,0xbf803f80,
0x3f803f80,0xbf803f80,0x3f803f80,0xbf803f80,0x3dc90000,0x3f7f3f80,0x3f463f35,0x3f223f35,0x3e953e48,0x3f753f7b,0x3f623f55,0x3ef13f0e,
0x3ef13ec4,0x3f623f6d,0x3f753f6d,0x3e953ec4,0x3f223f0e,0x3f463f55,0x3f7f3f7b,0x3dc93e48,0xbf7bbf80,0x3e480000,0x3e480000,0x3f7b3f80,
0xbf55bf6d,0x3f0e3ec4,0x3f0e3ec4,0x3f553f6d,0xbf0ebf35,0x3f553f35,0x3f553f35,0x3f0e3f35,0xbe48bec4,0x3f7b3f6d,0x3f7b3f6d,0x3e483ec4,
0xbe950000,0xbf75bf80,0xbef1bf35,0x3f623f35,0xbf46bf0e,0xbf22bf55,0x3dc9be48,0x3f7f3f7b,0xbf7fbf6d,0xbdc9bec4,0x3f223ec4,0x3f463f6d,
0xbf62bf7b,0x3ef13e48,0x3f753f55,0x3e953f0e,0x3f6d3f80,0xbec40000,0xbf6dbf80,0x3ec40000,0x3ec43f35,0xbf6dbf35,0xbec4bf35,0x3f6d3f35,
0xbec40000,0xbf6dbf80,0x3ec40000,0x3f6d3f80,0xbf6dbf35,0xbec4bf35,0x3f6d3f35,0x3ec43f35,0x3ef10000,0x3f623f80,0xbf75bf35,0xbe95bf35,
0x3f7f3f55,0x3dc93f0e,0xbf46bf7b,0x3f223e48,0x3f223f6d,0xbf46bec4,0x3dc9bec4,0x3f7f3f6d,0xbe953e48,0xbf75bf7b,0x3f623f0e,0x3ef13f55,
0xbf55bf80,0x3f0e0000,0xbf0e0000,0xbf55bf80,0x3e48bec4,0x3f7b3f6d,0xbf7bbf6d,0x3e48bec4,0x3f7b3f35,0x3e483f35,0xbe48bf35,0x3f7b3f35,
0x3f0e3f6d,0xbf55bec4,0x3f553ec4,0x3f0e3f6d,0xbf220000,0xbf46bf80,0x3dc93f35,0xbf7fbf35,0xbf62bf7b,0x3ef1be48,0xbf75bf0e,0xbe95bf55,
0x3e95bec4,0x3f753f6d,0xbef1bf6d,0x3f623ec4,0x3f7f3f55,0xbdc93f0e,0x3f463e48,0x3f223f7b,0x3f353f80,0xbf350000,0x3f353f80,0xbf350000,
0xbf350000,0xbf35bf80,0xbf350000,0xbf35bf80,0xbf35bf80,0x3f350000,0xbf35bf80,0x3f350000,0x3f350000,0x3f353f80,0x3f350000,0x3f353f80,
0x3f460000,0x3f223f80,0x3f7f3f35,0xbdc93f35,0x3ef13f7b,0xbf62be48,0xbe953f0e,0xbf75bf55,0xbf75bec4,0xbe95bf6d,0xbf62bf6d,0x3ef1bec4,
0xbdc9bf55,0x3f7f3f0e,0x3f22be48,0x3f463f7b,0xbf0ebf80,0x3f550000,0x3f550000,0x3f0e3f80,0x3f7b3ec4,0x3e483f6d,0x3e483f6d,0xbf7bbec4,
0xbe483f35,0xbf7bbf35,0xbf7bbf35,0x3e48bf35,0xbf55bf6d,0x3f0ebec4,0x3f0ebec4,0x3f553f6d,0xbf620000,0xbef1bf80,0x3e95bf35,0x3f753f35,
0x3dc9bf55,0x3f7f3f0e,0x3f223f7b,0xbf463e48,0x3f463f6d,0xbf223ec4,0xbf7fbec4,0xbdc9bf6d,0xbf75be48,0xbe95bf7b,0x3ef1bf0e,0x3f623f55,
0x3ec43f80,0xbf6d0000,0xbec4bf80,0x3f6d0000,0xbf6dbf35,0x3ec4bf35,0x3f6d3f35,0xbec43f35,0x3f6d0000,0x3ec43f80,0xbf6d0000,0xbec4bf80,
0xbec43f35,0xbf6dbf35,0x3ec4bf35,0x3f6d3f35,0x3f750000,0x3e953f80,0xbf62bf35,0x3ef1bf35,0xbf223f0e,0xbf46bf55,0x3f7f3e48,0x3dc93f7b,
0x3dc9bf6d,0x3f7f3ec4,0xbf463ec4,0xbf22bf6d,0x3ef13f7b,0xbf623e48,0x3e95bf55,0x3f753f0e,0xbe48bf80,0x3f7b0000,0xbf7b0000,0xbe48bf80,
0x3f0e3f6d,0xbf553ec4,0x3f55bec4,0x3f0e3f6d,0xbf55bf35,0x3f0ebf35,0xbf0e3f35,0xbf55bf35,0x3f7b3ec4,0xbe483f6d,0x3e48bf6d,0x3f7b3ec4,
0xbf7f0000,0xbdc9bf80,0xbf223f35,0xbf46bf35,0x3f75be48,0x3e953f7b,0x3ef1bf55,0x3f623f0e,0xbf623ec4,0xbef1bf6d,0xbe953f6d,0xbf75bec4,
0x3f46bf0e,0x3f223f55,0x3dc9bf7b,0x3f7f3e48,0x3f80,0xbf800000,0x3f80,0xbf800000,0xbf80,0x3f800000,0xbf80,0x3f800000,
0x3f80,0xbf800000,0x3f80,0xbf800000,0xbf80,0x3f800000,0xbf80,0x3f800000,0x3f7f0000,0xbdc93f80,0x3f223f35,0xbf463f35,
0xbf75be48,0x3e95bf7b,0xbef1bf55,0x3f62bf0e,0x3f623ec4,0xbef13f6d,0x3e953f6d,0xbf753ec4,0xbf46bf0e,0x3f22bf55,0xbdc9bf7b,0x3f7fbe48,
0x3e48bf80,0x3f7b0000,0x3f7b0000,0xbe483f80,0xbf0e3f6d,0xbf55bec4,0xbf55bec4,0x3f0ebf6d,0x3f55bf35,0x3f0e3f35,0x3f0e3f35,0xbf553f35,
0xbf7b3ec4,0xbe48bf6d,0xbe48bf6d,0x3f7bbec4,0xbf750000,0x3e95bf80,0x3f62bf35,0x3ef13f35,0x3f223f0e,0xbf463f55,0xbf7f3e48,0x3dc9bf7b,
0xbdc9bf6d,0x3f7fbec4,0x3f463ec4,0xbf223f6d,0xbef13f7b,0xbf62be48,0xbe95bf55,0x3f75bf0e,0xbec43f80,0xbf6d0000,0x3ec4bf80,0x3f6d0000,
0x3f6dbf35,0x3ec43f35,0xbf6d3f35,0xbec4bf35,0xbf6d0000,0x3ec4bf80,0x3f6d0000,0xbec43f80,0x3ec43f35,0xbf6d3f35,0xbec4bf35,0x3f6dbf35,
0x3f620000,0xbef13f80,0xbe95bf35,0x3f75bf35,0xbdc9bf55,0x3f7fbf0e,0xbf223f7b,0xbf46be48,0xbf463f6d,0xbf22bec4,0x3f7fbec4,0xbdc93f6d,
0x3f75be48,0xbe953f7b,0xbef1bf0e,0x3f62bf55,0x3f0ebf80,0x3f550000,0xbf550000,0x3f0ebf80,0xbf7b3ec4,0x3e48bf6d,0xbe483f6d,0xbf7b3ec4,
0x3e483f35,0xbf7b3f35,0x3f7bbf35,0x3e483f35,0x3f55bf6d,0x3f0e3ec4,0xbf0ebec4,0x3f55bf6d,0xbf460000,0x3f22bf80,0xbf7f3f35,0xbdc9bf35,
0xbef13f7b,0xbf623e48,0x3e953f0e,0xbf753f55,0x3f75bec4,0xbe953f6d,0x3f62bf6d,0x3ef13ec4,0x3dc9bf55,0x3f7fbf0e,0xbf22be48,0x3f46bf7b,
0xbf353f80,0xbf350000,0xbf353f80,0xbf350000,0x3f350000,0xbf353f80,0x3f350000,0xbf353f80,0x3f35bf80,0x3f350000,0x3f35bf80,0x3f350000,
0xbf350000,0x3f35bf80,0xbf350000,0x3f35bf80,0x3f220000,0xbf463f80,0xbdc93f35,0xbf7f3f35,0x3f62bf7b,0x3ef13e48,0x3f75bf0e,0xbe953f55,
0xbe95bec4,0x3f75bf6d,0x3ef1bf6d,0x3f62bec4,0xbf7f3f55,0xbdc9bf0e,0xbf463e48,0x3f22bf7b,0x3f55bf80,0x3f0e0000,0x3f0e0000,0xbf553f80,
0xbe48bec4,0x3f7bbf6d,0x3f7bbf6d,0x3e483ec4,0xbf7b3f35,0x3e48bf35,0x3e48bf35,0x3f7bbf35,0xbf0e3f6d,0xbf553ec4,0xbf553ec4,0x3f0ebf6d,
0xbef10000,0x3f62bf80,0x3f75bf35,0xbe953f35,0xbf7f3f55,0x3dc9bf0e,0x3f46bf7b,0x3f22be48,0xbf223f6d,0xbf463ec4,0xbdc9bec4,0x3f7fbf6d,
0x3e953e48,0xbf753f7b,0xbf623f0e,0x3ef1bf55,0xbf6d3f80,0xbec40000,0x3f6dbf80,0x3ec40000,0xbec43f35,0xbf6d3f35,0x3ec4bf35,0x3f6dbf35,
0x3ec40000,0xbf6d3f80,0xbec40000,0x3f6dbf80,0x3f6dbf35,0xbec43f35,0xbf6d3f35,0x3ec4bf35,0x3e950000,0xbf753f80,0x3ef1bf35,0x3f62bf35,
0x3f46bf0e,0xbf223f55,0xbdc9be48,0x3f7fbf7b,0x3f7fbf6d,0xbdc93ec4,0xbf223ec4,0x3f46bf6d,0x3f62bf7b,0x3ef1be48,0xbf753f55,0x3e95bf0e,
0x3f7bbf80,0x3e480000,0xbe480000,0x3f7bbf80,0x3f55bf6d,0x3f0ebec4,0xbf0e3ec4,0x3f55bf6d,0x3f0ebf35,0x3f55bf35,0xbf553f35,0x3f0ebf35,
0x3e48bec4,0x3f7bbf6d,0xbf7b3f6d,0x3e48bec4,0xbdc90000,0x3f7fbf80,0xbf463f35,0x3f22bf35,0xbe953e48,0x3f75bf7b,0xbf623f55,0x3ef1bf0e,
0xbef13ec4,0x3f62bf6d,0xbf753f6d,0x3e95bec4,0xbf223f0e,0x3f46bf55,0xbf7f3f7b,0x3dc9be48,0x40003f80,0x3fb53f80,0x3f80,0xbfb53f80,
0x40004000,0xbfb50000,0x0,0xbfb5c000,0x40004000,0xbfb5c000,0x0,0x3fb50000,0x40004000,0x3fb50000,0x0,0x3fb54000,
0x3fff3f80,0x3fa23f80,0xbe49bf80,0xbfc6bf80,0x3ff53ffb,0xbfe2bec8,0xbf15bec8,0xbf71bffb,0x3fe23fed,0xbf15bfed,0xbf71bf44,0x3ff53f44,
0x3fc63fd5,0x3fff3f8e,0xbfa2bf8e,0x3e493fd5,0x3ffb3f80,0x3f8e3f80,0xbec83f80,0xbfd53f80,0x3fd53fed,0xbffbbf44,0xbf8ebf44,0xbec8bfed,
0x3f8e3fb5,0x3ec8bfb5,0xbfd5bfb5,0x3ffb3fb5,0x3ec83f44,0x3fd53fed,0xbffbbfed,0xbf8e3f44,0x3ff53f80,0x3f713f80,0xbf15bf80,0xbfe2bf80,
0x3fa23fd5,0xbfffbf8e,0xbfc6bf8e,0x3e49bfd5,0x3e493f44,0x3fa2bf44,0xbfffbfed,0x3fc63fed,0xbf71bec8,0x3f153ffb,0xbfe2bffb,0xbff5bec8,
0x3fed3f80,0x3f443f80,0xbf443f80,0xbfed3f80,0x3f443fb5,0xbfedbfb5,0xbfedbfb5,0x3f44bfb5,0xbf440000,0x3fed0000,0xbfedc000,0x3f444000,
0xbfedbfb5,0xbf443fb5,0xbf44bfb5,0xbfedbfb5,0x3fe23f80,0x3f153f80,0xbf71bf80,0xbff5bf80,0x3e493f8e,0xbfc6bfd5,0xbfffbfd5,0x3fa2bf8e,
0xbfc6bf44,0x3fff3f44,0xbfa2bfed,0xbe493fed,0xbff5bffb,0xbfe23ec8,0x3f15bec8,0xbf71bffb,0x3fd53f80,0x3ec83f80,0xbf8e3f80,0xbffb3f80,
0xbec83f44,0xbf8ebfed,0xbffbbfed,0x3fd5bf44,0xbffbbfb5,0x3fd53fb5,0xbec8bfb5,0xbf8e3fb5,0xbf8ebfed,0xbffbbf44,0x3fd53f44,0x3ec8bfed,
0x3fc63f80,0x3e493f80,0xbfa2bf80,0xbfffbf80,0xbf713ec8,0xbf15bffb,0xbfe2bffb,0x3ff5bec8,0xbff5bfed,0x3f713fed,0x3f15bf44,0xbfe23f44,
0x3e49bf8e,0xbfa2bfd5,0x3fff3fd5,0x3fc6bf8e,0x3f80,0xbfb53f80,0xc0003f80,0xbfb53f80,0xc000,0x3fb50000,0x40000000,0xbfb54000,
0x4000,0x3fb5c000,0xc0000000,0x3fb50000,0xc000,0xbfb50000,0x40000000,0x3fb5c000,0xbe493f80,0xbfc63f80,0xbfffbf80,0xbfa2bf80,
0x3f15bffb,0x3f713ec8,0x3ff53ec8,0xbfe23ffb,0xbf713fed,0x3ff5bfed,0xbfe2bf44,0x3f153f44,0x3fa2bfd5,0xbe49bf8e,0x3fc63f8e,0x3fffbfd5,
0xbec83f80,0xbfd53f80,0xbffb3f80,0xbf8e3f80,0x3f8ebfed,0x3ec83f44,0x3fd53f44,0xbffb3fed,0xbfd53fb5,0x3ffbbfb5,0xbf8ebfb5,0xbec83fb5,
0x3ffbbf44,0x3f8ebfed,0x3ec83fed,0x3fd5bf44,0xbf153f80,0xbfe23f80,0xbff5bf80,0xbf71bf80,0x3fc6bfd5,0xbe493f8e,0x3fa23f8e,0xbfff3fd5,
0xbfff3f44,0x3fc6bf44,0xbe49bfed,0xbfa23fed,0x3fe23ec8,0x3ff5bffb,0xbf713ffb,0x3f153ec8,0xbf443f80,0xbfed3f80,0xbfed3f80,0xbf443f80,
0x3fedbfb5,0xbf443fb5,0x3f443fb5,0xbfed3fb5,0xbfed0000,0x3f440000,0x3f44c000,0xbfed4000,0x3f443fb5,0x3fedbfb5,0xbfed3fb5,0xbf443fb5,
0xbf713f80,0xbff53f80,0xbfe2bf80,0xbf15bf80,0x3fffbf8e,0xbfa23fd5,0x3e493fd5,0xbfc63f8e,0xbfa2bf44,0xbe493f44,0x3fc6bfed,0xbfff3fed,
0xbf153ffb,0x3f71bec8,0xbff53ec8,0xbfe23ffb,0xbf8e3f80,0xbffb3f80,0xbfd53f80,0xbec83f80,0x3ffbbf44,0xbfd53fed,0xbec83fed,0xbf8e3f44,
0xbec8bfb5,0xbf8e3fb5,0x3ffbbfb5,0xbfd53fb5,0xbfd53fed,0xbec83f44,0xbf8ebf44,0xbffb3fed,0xbfa23f80,0xbfff3f80,0xbfc6bf80,0xbe49bf80,
0x3fe2bec8,0xbff53ffb,0xbf713ffb,0xbf153ec8,0x3f15bfed,0xbfe23fed,0x3ff5bf44,0xbf713f44,0xbfff3f8e,0xbfc63fd5,0x3e49bfd5,0xbfa23f8e,
0xc0003f80,0xbfb53f80,0x3f80,0x3fb53f80,0xc0004000,0x3fb50000,0x0,0x3fb5c000,0xc0004000,0x3fb5c000,0x0,0xbfb50000,
0xc0004000,0xbfb50000,0x0,0xbfb54000,0xbfff3f80,0xbfa23f80,0x3e49bf80,0x3fc6bf80,0xbff53ffb,0x3fe2bec8,0x3f15bec8,0x3f71bffb,
0xbfe23fed,0x3f15bfed,0x3f71bf44,0xbff53f44,0xbfc63fd5,0xbfff3f8e,0x3fa2bf8e,0xbe493fd5,0xbffb3f80,0xbf8e3f80,0x3ec83f80,0x3fd53f80,
0xbfd53fed,0x3ffbbf44,0x3f8ebf44,0x3ec8bfed,0xbf8e3fb5,0xbec8bfb5,0x3fd5bfb5,0xbffb3fb5,0xbec83f44,0xbfd53fed,0x3ffbbfed,0x3f8e3f44,
0xbff53f80,0xbf713f80,0x3f15bf80,0x3fe2bf80,0xbfa23fd5,0x3fffbf8e,0x3fc6bf8e,0xbe49bfd5,0xbe493f44,0xbfa2bf44,0x3fffbfed,0xbfc63fed,
0x3f71bec8,0xbf153ffb,0x3fe2bffb,0x3ff5bec8,0xbfed3f80,0xbf443f80,0x3f443f80,0x3fed3f80,0xbf443fb5,0x3fedbfb5,0x3fedbfb5,0xbf44bfb5,
0x3f440000,0xbfed0000,0x3fedc000,0xbf444000,0x3fedbfb5,0x3f443fb5,0x3f44bfb5,0x3fedbfb5,0xbfe23f80,0xbf153f80,0x3f71bf80,0x3ff5bf80,
0xbe493f8e,0x3fc6bfd5,0x3fffbfd5,0xbfa2bf8e,0x3fc6bf44,0xbfff3f44,0x3fa2bfed,0x3e493fed,0x3ff5bffb,0x3fe23ec8,0xbf15bec8,0x3f71bffb,
0xbfd53f80,0xbec83f80,0x3f8e3f80,0x3ffb3f80,0x3ec83f44,0x3f8ebfed,0x3ffbbfed,0xbfd5bf44,0x3ffbbfb5,0xbfd53fb5,0x3ec8bfb5,0x3f8e3fb5,
0x3f8ebfed,0x3ffbbf44,0xbfd53f44,0xbec8bfed,0xbfc63f80,0xbe493f80,0x3fa2bf80,0x3fffbf80,0x3f713ec8,0x3f15bffb,0x3fe2bffb,0xbff5bec8,
0x3ff5bfed,0xbf713fed,0xbf15bf44,0x3fe23f44,0xbe49bf8e,0x3fa2bfd5,0xbfff3fd5,0xbfc6bf8e,0x3f80,0x3fb53f80,0x40003f80,0x3fb53f80,
0xc000,0xbfb50000,0xc0000000,0x3fb54000,0x4000,0xbfb5c000,0x40000000,0xbfb50000,0xc000,0x3fb50000,0xc0000000,0xbfb5c000,
0x3e493f80,0x3fc63f80,0x3fffbf80,0x3fa2bf80,0xbf15bffb,0xbf713ec8,0xbff53ec8,0x3fe23ffb,0x3f713fed,0xbff5bfed,0x3fe2bf44,0xbf153f44,
0xbfa2bfd5,0x3e49bf8e,0xbfc63f8e,0xbfffbfd5,0x3ec83f80,0x3fd53f80,0x3ffb3f80,0x3f8e3f80,0xbf8ebfed,0xbec83f44,0xbfd53f44,0x3ffb3fed,
0x3fd53fb5,0xbffbbfb5,0x3f8ebfb5,0x3ec83fb5,0xbffbbf44,0xbf8ebfed,0xbec83fed,0xbfd5bf44,0x3f153f80,0x3fe23f80,0x3ff5bf80,0x3f71bf80,
0xbfc6bfd5,0x3e493f8e,0xbfa23f8e,0x3fff3fd5,0x3fff3f44,0xbfc6bf44,0x3e49bfed,0x3fa23fed,0xbfe23ec8,0xbff5bffb,0x3f713ffb,0xbf153ec8,
0x3f443f80,0x3fed3f80,0x3fed3f80,0x3f443f80,0xbfedbfb5,0x3f443fb5,0xbf443fb5,0x3fed3fb5,0x3fed0000,0xbf440000,0xbf44c000,0x3fed4000,
0xbf443fb5,0xbfedbfb5,0x3fed3fb5,0x3f443fb5,0x3f713f80,0x3ff53f80,0x3fe2bf80,0x3f15bf80,0xbfffbf8e,0x3fa23fd5,0xbe493fd5,0x3fc63f8e,
0x3fa2bf44,0x3e493f44,0xbfc6bfed,0x3fff3fed,0x3f153ffb,0xbf71bec8,0x3ff53ec8,0x3fe23ffb,0x3f8e3f80,0x3ffb3f80,0x3fd53f80,0x3ec83f80,
0xbffbbf44,0x3fd53fed,0x3ec83fed,0x3f8e3f44,0x3ec8bfb5,0x3f8e3fb5,0xbffbbfb5,0x3fd53fb5,0x3fd53fed,0x3ec83f44,0x3f8ebf44,0x3ffb3fed,
0x3fa23f80,0x3fff3f80,0x3fc6bf80,0x3e49bf80,0xbfe2bec8,0x3ff53ffb,0x3f713ffb,0x3f153ec8,0xbf15bfed,0x3fe23fed,0xbff5bf44,0x3f713f44,
0x3fff3f8e,0x3fc63fd5,0xbe49bfd5,0x3fa23f8e,0x40004000,0x3fb54000,0x0,0xbfb50000,0x40004000,0xbfb50000,0x0,0xbfb5c000,
0x40004000,0xbfb5c000,0x0,0x3fb50000,0x40004000,0x3fb50000,0x0,0x3fb54000,0x3fa23fb5,0xbe493fb5,0xbfc6bfb5,0xbfffbfb5,
0x3f713f8e,0xbff5bfd5,0xbfe2bfd5,0x3f15bf8e,0x3f153f44,0x3f71bf44,0xbff5bfed,0x3fe23fed,0x3e493ec8,0x3fc63ffb,0xbfffbffb,0xbfa23ec8,
0xbec80000,0xbfd50000,0xbffbc000,0xbf8ec000,0xbf8ebf44,0xbec8bfed,0xbfd5bfed,0x3ffb3f44,0xbfd5bfb5,0x3ffb3fb5,0xbf8ebfb5,0xbec83fb5,
0xbffbbfed,0xbf8e3f44,0xbec8bf44,0xbfd5bfed,0xbfe2bfb5,0xbff5bfb5,0xbf71bfb5,0x3f15bfb5,0xbfffbffb,0x3fc6bec8,0x3e49bec8,0x3fa23ffb,
0xbfc6bfed,0x3e493fed,0x3fa23f44,0xbfffbf44,0xbf15bf8e,0xbfe2bfd5,0x3ff53fd5,0x3f71bf8e,0xbfedc000,0xbf44c000,0x3f440000,0x3fed0000,
0xbf44bfb5,0x3fed3fb5,0x3fed3fb5,0xbf443fb5,0x3f440000,0xbfed0000,0x3fed4000,0xbf44c000,0x3fed3fb5,0x3f44bfb5,0x3f443fb5,0x3fed3fb5,
0xbf15bfb5,0x3f71bfb5,0x3ff53fb5,0x3fe23fb5,0x3fa23ec8,0x3e493ffb,0x3fc63ffb,0xbfffbec8,0x3fff3fed,0xbfa2bfed,0xbe493f44,0x3fc6bf44,
0x3f713fd5,0x3ff53f8e,0xbfe2bf8e,0xbf153fd5,0x3f8e0000,0x3ffb0000,0x3fd54000,0x3ec84000,0x3ffb3fed,0xbfd53f44,0xbec83f44,0xbf8ebfed,
0x3ec83fb5,0x3f8ebfb5,0xbffbbfb5,0x3fd53fb5,0xbfd5bf44,0xbec83fed,0xbf8ebfed,0xbffbbf44,0x3fff3fb5,0x3fc63fb5,0x3e493fb5,0xbfa23fb5,
0x3f153fd5,0xbfe2bf8e,0xbff5bf8e,0x3f71bfd5,0xbfe2bf44,0x3ff53f44,0xbf71bfed,0xbf153fed,0xbfa2bffb,0xbfffbec8,0x3fc63ec8,0x3e49bffb,
0x4000,0xbfb54000,0xc0000000,0xbfb50000,0xc000,0x3fb50000,0x40000000,0xbfb54000,0x4000,0x3fb5c000,0xc0000000,0x3fb50000,
0xc000,0xbfb50000,0x40000000,0x3fb5c000,0xbfc63fb5,0xbfff3fb5,0xbfa2bfb5,0x3e49bfb5,0x3fe2bf8e,0xbf153fd5,0x3f713fd5,0xbff53f8e,
0xbff53f44,0x3fe2bf44,0xbf15bfed,0xbf713fed,0x3fffbec8,0x3fa2bffb,0x3e493ffb,0x3fc6bec8,0xbffb0000,0xbf8e0000,0x3ec8c000,0x3fd5c000,
0x3fd53f44,0xbffb3fed,0xbf8e3fed,0xbec8bf44,0xbf8ebfb5,0xbec83fb5,0x3fd5bfb5,0xbffb3fb5,0x3ec83fed,0x3fd5bf44,0xbffb3f44,0xbf8e3fed,
0xbf71bfb5,0x3f15bfb5,0x3fe2bfb5,0x3ff5bfb5,0xbe493ffb,0xbfa23ec8,0xbfff3ec8,0x3fc6bffb,0x3fa2bfed,0xbfff3fed,0x3fc63f44,0xbe49bf44,
0xbff53f8e,0xbf713fd5,0xbf15bfd5,0xbfe23f8e,0x3f44c000,0x3fedc000,0x3fed0000,0x3f440000,0xbfed3fb5,0x3f44bfb5,0xbf44bfb5,0x3fedbfb5,
0x3fed0000,0xbf440000,0xbf444000,0x3fedc000,0xbf44bfb5,0xbfed3fb5,0x3fedbfb5,0x3f44bfb5,0x3ff5bfb5,0x3fe2bfb5,0x3f153fb5,0xbf713fb5,
0xbfc6bec8,0x3fffbffb,0x3fa2bffb,0x3e493ec8,0xbe493fed,0x3fc6bfed,0xbfff3f44,0x3fa2bf44,0x3fe2bfd5,0x3f15bf8e,0x3f713f8e,0x3ff5bfd5,
0x3fd50000,0x3ec80000,0xbf8e4000,0xbffb4000,0x3ec8bfed,0x3f8ebf44,0x3ffbbf44,0xbfd53fed,0xbffb3fb5,0x3fd5bfb5,0xbec8bfb5,0xbf8e3fb5,
0x3f8e3f44,0x3ffbbfed,0xbfd53fed,0xbec83f44,0x3e493fb5,0xbfa23fb5,0xbfff3fb5,0xbfc63fb5,0x3ff5bfd5,0xbf713f8e,0x3f153f8e,0xbfe23fd5,
0xbf71bf44,0xbf153f44,0x3fe2bfed,0xbff53fed,0xbfc63ffb,0xbe493ec8,0xbfa2bec8,0xbfff3ffb,0xc0004000,0xbfb54000,0x0,0x3fb50000,
0xc0004000,0x3fb50000,0x0,0x3fb5c000,0xc0004000,0x3fb5c000,0x0,0xbfb50000,0xc0004000,0xbfb50000,0x0,0xbfb54000,
0xbfa23fb5,0x3e493fb5,0x3fc6bfb5,0x3fffbfb5,0xbf713f8e,0x3ff5bfd5,0x3fe2bfd5,0xbf15bf8e,0xbf153f44,0xbf71bf44,0x3ff5bfed,0xbfe23fed,
0xbe493ec8,0xbfc63ffb,0x3fffbffb,0x3fa23ec8,0x3ec80000,0x3fd50000,0x3ffbc000,0x3f8ec000,0x3f8ebf44,0x3ec8bfed,0x3fd5bfed,0xbffb3f44,
0x3fd5bfb5,0xbffb3fb5,0x3f8ebfb5,0x3ec83fb5,0x3ffbbfed,0x3f8e3f44,0x3ec8bf44,0x3fd5bfed,0x3fe2bfb5,0x3ff5bfb5,0x3f71bfb5,0xbf15bfb5,
0x3fffbffb,0xbfc6bec8,0xbe49bec8,0xbfa23ffb,0x3fc6bfed,0xbe493fed,0xbfa23f44,0x3fffbf44,0x3f15bf8e,0x3fe2bfd5,0xbff53fd5,0xbf71bf8e,
0x3fedc000,0x3f44c000,0xbf440000,0xbfed0000,0x3f44bfb5,0xbfed3fb5,0xbfed3fb5,0x3f443fb5,0xbf440000,0x3fed0000,0xbfed4000,0x3f44c000,
0xbfed3fb5,0xbf44bfb5,0xbf443fb5,0xbfed3fb5,0x3f15bfb5,0xbf71bfb5,0xbff53fb5,0xbfe23fb5,0xbfa23ec8,0xbe493ffb,0xbfc63ffb,0x3fffbec8,
0xbfff3fed,0x3fa2bfed,0x3e493f44,0xbfc6bf44,0xbf713fd5,0xbff53f8e,0x3fe2bf8e,0x3f153fd5,0xbf8e0000,0xbffb0000,0xbfd54000,0xbec84000,
0xbffb3fed,0x3fd53f44,0x3ec83f44,0x3f8ebfed,0xbec83fb5,0xbf8ebfb5,0x3ffbbfb5,0xbfd53fb5,0x3fd5bf44,0x3ec83fed,0x3f8ebfed,0x3ffbbf44,
0xbfff3fb5,0xbfc63fb5,0xbe493fb5,0x3fa23fb5,0xbf153fd5,0x3fe2bf8e,0x3ff5bf8e,0xbf71bfd5,0x3fe2bf44,0xbff53f44,0x3f71bfed,0x3f153fed,
0x3fa2bffb,0x3fffbec8,0xbfc63ec8,0xbe49bffb,0x4000,0x3fb54000,0x40000000,0x3fb50000,0xc000,0xbfb50000,0xc0000000,0x3fb54000,
0x4000,0xbfb5c000,0x40000000,0xbfb50000,0xc000,0x3fb50000,0xc0000000,0xbfb5c000,0x3fc63fb5,0x3fff3fb5,0x3fa2bfb5,0xbe49bfb5,
0xbfe2bf8e,0x3f153fd5,0xbf713fd5,0x3ff53f8e,0x3ff53f44,0xbfe2bf44,0x3f15bfed,0x3f713fed,0xbfffbec8,0xbfa2bffb,0xbe493ffb,0xbfc6bec8,
0x3ffb0000,0x3f8e0000,0xbec8c000,0xbfd5c000,0xbfd53f44,0x3ffb3fed,0x3f8e3fed,0x3ec8bf44,0x3f8ebfb5,0x3ec83fb5,0xbfd5bfb5,0x3ffb3fb5,
0xbec83fed,0xbfd5bf44,0x3ffb3f44,0x3f8e3fed,0x3f71bfb5,0xbf15bfb5,0xbfe2bfb5,0xbff5bfb5,0x3e493ffb,0x3fa23ec8,0x3fff3ec8,0xbfc6bffb,
0xbfa2bfed,0x3fff3fed,0xbfc63f44,0x3e49bf44,0x3ff53f8e,0x3f713fd5,0x3f15bfd5,0x3fe23f8e,0xbf44c000,0xbfedc000,0xbfed0000,0xbf440000,
0x3fed3fb5,0xbf44bfb5,0x3f44bfb5,0xbfedbfb5,0xbfed0000,0x3f440000,0x3f444000,0xbfedc000,0x3f44bfb5,0x3fed3fb5,0xbfedbfb5,0xbf44bfb5,
0xbff5bfb5,0xbfe2bfb5,0xbf153fb5,0x3f713fb5,0x3fc6bec8,0xbfffbffb,0xbfa2bffb,0xbe493ec8,0x3e493fed,0xbfc6bfed,0x3fff3f44,0xbfa2bf44,
0xbfe2bfd5,0xbf15bf8e,0xbf713f8e,0xbff5bfd5,0xbfd50000,0xbec80000,0x3f8e4000,0x3ffb4000,0xbec8bfed,0xbf8ebf44,0xbffbbf44,0x3fd53fed,
0x3ffb3fb5,0xbfd5bfb5,0x3ec8bfb5,0x3f8e3fb5,0xbf8e3f44,0xbffbbfed,0x3fd53fed,0x3ec83f44,0xbe493fb5,0x3fa23fb5,0x3fff3fb5,0x3fc63fb5,
0xbff5bfd5,0x3f713f8e,0xbf153f8e,0x3fe23fd5,0x3f71bf44,0x3f153f44,0xbfe2bfed,0x3ff53fed,0x3fc63ffb,0x3e493ec8,0x3fa2bec8,0x3fff3ffb,
0x40004000,0x3fb54000,0x0,0xbfb50000,0x40004000,0xbfb50000,0x0,0xbfb5c000,0x40004000,0xbfb5c000,0x0,0x3fb50000,
0x40004000,0x3fb50000,0x0,0x3fb54000,0xbe490000,0xbfc60000,0xbfffc000,0xbfa2c000,0xbf15bec8,0xbf71bffb,0xbff5bffb,0x3fe23ec8,
0xbf71bf44,0x3ff53f44,0xbfe2bfed,0x3f153fed,0xbfa2bf8e,0x3e493fd5,0xbfc6bfd5,0xbfffbf8e,0xbffbc000,0xbf8ec000,0x3ec80000,0x3fd50000,
0xbfd5bfed,0x3ffb3f44,0x3f8e3f44,0x3ec83fed,0xbf8ebfb5,0xbec83fb5,0x3fd53fb5,0xbffbbfb5,0xbec8bf44,0xbfd5bfed,0x3ffb3fed,0x3f8ebf44,
0x3f150000,0x3fe20000,0x3ff54000,0x3f714000,0x3fc63f8e,0xbe493fd5,0x3fa23fd5,0xbfffbf8e,0x3fff3fed,0xbfc6bfed,0x3e493f44,0x3fa2bf44,
0x3fe23ffb,0x3ff53ec8,0xbf71bec8,0x3f153ffb,0x3fed4000,0x3f444000,0xbf440000,0xbfed0000,0x3f443fb5,0xbfedbfb5,0xbfedbfb5,0x3f44bfb5,
0xbf440000,0x3fed0000,0xbfedc000,0x3f444000,0xbfedbfb5,0xbf443fb5,0xbf44bfb5,0xbfedbfb5,0xbf710000,0xbff50000,0xbfe2c000,0xbf15c000,
0xbfffbfd5,0x3fa2bf8e,0xbe49bf8e,0x3fc63fd5,0xbfa2bfed,0xbe493fed,0x3fc63f44,0xbfffbf44,0x3f15bec8,0xbf71bffb,0x3ff53ffb,0x3fe2bec8,
0xbfd5c000,0xbec8c000,0x3f8e0000,0x3ffb0000,0x3ec8bf44,0x3f8e3fed,0x3ffb3fed,0xbfd53f44,0x3ffb3fb5,0xbfd5bfb5,0x3ec83fb5,0x3f8ebfb5,
0x3f8e3fed,0x3ffb3f44,0xbfd5bf44,0xbec83fed,0x3fa20000,0x3fff0000,0x3fc64000,0x3e494000,0x3fe23ffb,0xbff53ec8,0xbf713ec8,0xbf15bffb,
0xbf153f44,0x3fe2bf44,0xbff5bfed,0x3f713fed,0xbfffbfd5,0xbfc63f8e,0x3e49bf8e,0xbfa2bfd5,0x4000,0xbfb54000,0xc0000000,0xbfb50000,
0xc000,0x3fb50000,0x40000000,0xbfb54000,0x4000,0x3fb5c000,0xc0000000,0x3fb50000,0xc000,0xbfb50000,0x40000000,0x3fb5c000,
0xbfff0000,0xbfa20000,0x3e49c000,0x3fc6c000,0x3ff53ec8,0xbfe23ffb,0xbf153ffb,0xbf71bec8,0xbfe2bf44,0x3f153f44,0x3f71bfed,0xbff53fed,
0x3fc63f8e,0x3fffbfd5,0xbfa23fd5,0x3e493f8e,0x3ec8c000,0x3fd5c000,0x3ffb0000,0x3f8e0000,0xbf8e3fed,0xbec8bf44,0xbfd5bf44,0x3ffbbfed,
0x3fd5bfb5,0xbffb3fb5,0x3f8e3fb5,0x3ec8bfb5,0xbffb3f44,0xbf8e3fed,0xbec8bfed,0xbfd53f44,0x3ff50000,0x3f710000,0xbf154000,0xbfe24000,
0xbfa2bf8e,0x3fffbfd5,0x3fc6bfd5,0xbe493f8e,0x3e493fed,0x3fa2bfed,0xbfff3f44,0x3fc6bf44,0x3f71bffb,0xbf15bec8,0x3fe23ec8,0x3ff5bffb,
0xbf444000,0xbfed4000,0xbfed0000,0xbf440000,0x3fedbfb5,0xbf443fb5,0x3f443fb5,0xbfed3fb5,0xbfed0000,0x3f440000,0x3f44c000,0xbfed4000,
0x3f443fb5,0x3fedbfb5,0xbfed3fb5,0xbf443fb5,0xbfe20000,0xbf150000,0x3f71c000,0x3ff5c000,0x3e493fd5,0xbfc63f8e,0xbfff3f8e,0x3fa2bfd5,
0x3fc6bfed,0xbfff3fed,0x3fa23f44,0x3e49bf44,0xbff53ec8,0xbfe23ffb,0x3f15bffb,0xbf713ec8,0x3f8ec000,0x3ffbc000,0x3fd50000,0x3ec80000,
0xbffb3f44,0x3fd5bfed,0x3ec8bfed,0x3f8ebf44,0x3ec83fb5,0x3f8ebfb5,0xbffb3fb5,0x3fd5bfb5,0x3fd5bfed,0x3ec8bf44,0x3f8e3f44,0x3ffbbfed,
0x3fc60000,0x3e490000,0xbfa24000,0xbfff4000,0x3f71bffb,0x3f15bec8,0x3fe2bec8,0xbff53ffb,0xbff53f44,0x3f71bf44,0x3f15bfed,0xbfe23fed,
0xbe493fd5,0x3fa2bf8e,0xbfff3f8e,0xbfc63fd5,0xc0004000,0xbfb54000,0x0,0x3fb50000,0xc0004000,0x3fb50000,0x0,0x3fb5c000,
0xc0004000,0x3fb5c000,0x0,0xbfb50000,0xc0004000,0xbfb50000,0x0,0xbfb54000,0x3e490000,0x3fc60000,0x3fffc000,0x3fa2c000,
0x3f15bec8,0x3f71bffb,0x3ff5bffb,0xbfe23ec8,0x3f71bf44,0xbff53f44,0x3fe2bfed,0xbf153fed,0x3fa2bf8e,0xbe493fd5,0x3fc6bfd5,0x3fffbf8e,
0x3ffbc000,0x3f8ec000,0xbec80000,0xbfd50000,0x3fd5bfed,0xbffb3f44,0xbf8e3f44,0xbec83fed,0x3f8ebfb5,0x3ec83fb5,0xbfd53fb5,0x3ffbbfb5,
0x3ec8bf44,0x3fd5bfed,0xbffb3fed,0xbf8ebf44,0xbf150000,0xbfe20000,0xbff54000,0xbf714000,0xbfc63f8e,0x3e493fd5,0xbfa23fd5,0x3fffbf8e,
0xbfff3fed,0x3fc6bfed,0xbe493f44,0xbfa2bf44,0xbfe23ffb,0xbff53ec8,0x3f71bec8,0xbf153ffb,0xbfed4000,0xbf444000,0x3f440000,0x3fed0000,
0xbf443fb5,0x3fedbfb5,0x3fedbfb5,0xbf44bfb5,0x3f440000,0xbfed0000,0x3fedc000,0xbf444000,0x3fedbfb5,0x3f443fb5,0x3f44bfb5,0x3fedbfb5,
0x3f710000,0x3ff50000,0x3fe2c000,0x3f15c000,0x3fffbfd5,0xbfa2bf8e,0x3e49bf8e,0xbfc63fd5,0x3fa2bfed,0x3e493fed,0xbfc63f44,0x3fffbf44,
0xbf15bec8,0x3f71bffb,0xbff53ffb,0xbfe2bec8,0x3fd5c000,0x3ec8c000,0xbf8e0000,0xbffb0000,0xbec8bf44,0xbf8e3fed,0xbffb3fed,0x3fd53f44,
0xbffb3fb5,0x3fd5bfb5,0xbec83fb5,0xbf8ebfb5,0xbf8e3fed,0xbffb3f44,0x3fd5bf44,0x3ec83fed,0xbfa20000,0xbfff0000,0xbfc64000,0xbe494000,
0xbfe23ffb,0x3ff53ec8,0x3f713ec8,0x3f15bffb,0x3f153f44,0xbfe2bf44,0x3ff5bfed,0xbf713fed,0x3fffbfd5,0x3fc63f8e,0xbe49bf8e,0x3fa2bfd5,
0x4000,0x3fb54000,0x40000000,0x3fb50000,0xc000,0xbfb50000,0xc0000000,0x3fb54000,0x4000,0xbfb5c000,0x40000000,0xbfb50000,
0xc000,0x3fb50000,0xc0000000,0xbfb5c000,0x3fff0000,0x3fa20000,0xbe49c000,0xbfc6c000,0xbff53ec8,0x3fe23ffb,0x3f153ffb,0x3f71bec8,
0x3fe2bf44,0xbf153f44,0xbf71bfed,0x3ff53fed,0xbfc63f8e,0xbfffbfd5,0x3fa23fd5,0xbe493f8e,0xbec8c000,0xbfd5c000,0xbffb0000,0xbf8e0000,
0x3f8e3fed,0x3ec8bf44,0x3fd5bf44,0xbffbbfed,0xbfd5bfb5,0x3ffb3fb5,0xbf8e3fb5,0xbec8bfb5,0x3ffb3f44,0x3f8e3fed,0x3ec8bfed,0x3fd53f44,
0xbff50000,0xbf710000,0x3f154000,0x3fe24000,0x3fa2bf8e,0xbfffbfd5,0xbfc6bfd5,0x3e493f8e,0xbe493fed,0xbfa2bfed,0x3fff3f44,0xbfc6bf44,
0xbf71bffb,0x3f15bec8,0xbfe23ec8,0xbff5bffb,0x3f444000,0x3fed4000,0x3fed0000,0x3f440000,0xbfedbfb5,0x3f443fb5,0xbf443fb5,0x3fed3fb5,
0x3fed0000,0xbf440000,0xbf44c000,0x3fed4000,0xbf443fb5,0xbfedbfb5,0x3fed3fb5,0x3f443fb5,0x3fe20000,0x3f150000,0xbf71c000,0xbff5c000,
0xbe493fd5,0x3fc63f8e,0x3fff3f8e,0xbfa2bfd5,0xbfc6bfed,0x3fff3fed,0xbfa23f44,0xbe49bf44,0x3ff53ec8,0x3fe23ffb,0xbf15bffb,0x3f713ec8,
0xbf8ec000,0xbffbc000,0xbfd50000,0xbec80000,0x3ffb3f44,0xbfd5bfed,0xbec8bfed,0xbf8ebf44,0xbec83fb5,0xbf8ebfb5,0x3ffb3fb5,0xbfd5bfb5,
0xbfd5bfed,0xbec8bf44,0xbf8e3f44,0xbffbbfed,0xbfc60000,0xbe490000,0x3fa24000,0x3fff4000,0xbf71bffb,0xbf15bec8,0xbfe2bec8,0x3ff53ffb,
0x3ff53f44,0xbf71bf44,0xbf15bfed,0x3fe23fed,0x3e493fd5,0xbfa2bf8e,0x3fff3f8e,0x3fc63fd5,0x40004000,0x3fb54000,0x0,0xbfb50000,
0x40004000,0xbfb50000,0x0,0xbfb5c000,0x40004000,0xbfb5c000,0x0,0x3fb50000,0x40004000,0x3fb50000,0x0,0x3fb54000,
0xbfc6bfb5,0xbfffbfb5,0xbfa2bfb5,0x3e49bfb5,0xbfe2bfd5,0x3f15bf8e,0xbf71bf8e,0x3ff53fd5,0xbff5bfed,0x3fe23fed,0xbf15bf44,0xbf713f44,
0xbfffbffb,0xbfa23ec8,0xbe49bec8,0xbfc6bffb,0x3ec80000,0x3fd50000,0x3ffb4000,0x3f8e4000,0x3f8e3f44,0x3ec83fed,0x3fd53fed,0xbffbbf44,
0x3fd53fb5,0xbffbbfb5,0x3f8e3fb5,0x3ec8bfb5,0x3ffb3fed,0x3f8ebf44,0x3ec83f44,0x3fd53fed,0x3f713fb5,0xbf153fb5,0xbfe2bfb5,0xbff5bfb5,
0xbe493ec8,0xbfa2bffb,0xbfffbffb,0x3fc6bec8,0xbfa2bf44,0x3fff3f44,0xbfc6bfed,0x3e493fed,0xbff5bfd5,0xbf713f8e,0xbf15bf8e,0xbfe2bfd5,
0xbfedc000,0xbf44c000,0x3f440000,0x3fed0000,0xbf44bfb5,0x3fed3fb5,0x3fed3fb5,0xbf443fb5,0x3f440000,0xbfed0000,0x3fed4000,0xbf44c000,
0x3fed3fb5,0x3f44bfb5,0x3f443fb5,0x3fed3fb5,0x3ff53fb5,0x3fe23fb5,0x3f153fb5,0xbf713fb5,0x3fc63ffb,0xbfffbec8,0xbfa2bec8,0xbe49bffb,
0xbe493f44,0x3fc6bf44,0xbfffbfed,0x3fa23fed,0xbfe2bf8e,0xbf153fd5,0xbf71bfd5,0xbff5bf8e,0xbf8e0000,0xbffb0000,0xbfd5c000,0xbec8c000,
0xbffbbfed,0x3fd5bf44,0x3ec8bf44,0x3f8e3fed,0xbec8bfb5,0xbf8e3fb5,0x3ffb3fb5,0xbfd5bfb5,0x3fd53f44,0x3ec8bfed,0x3f8e3fed,0x3ffb3f44,
0xbe49bfb5,0x3fa2bfb5,0x3fff3fb5,0x3fc63fb5,0x3ff53f8e,0xbf713fd5,0x3f153fd5,0xbfe2bf8e,0x3f713fed,0x3f15bfed,0xbfe2bf44,0x3ff53f44,
0xbfc6bec8,0xbe493ffb,0xbfa2bffb,0xbfffbec8,0x4000,0xbfb54000,0xc0000000,0xbfb50000,0xc000,0x3fb50000,0x40000000,0xbfb54000,
0x4000,0x3fb5c000,0xc0000000,0x3fb50000,0xc000,0xbfb50000,0x40000000,0x3fb5c000,0xbfa2bfb5,0x3e49bfb5,0x3fc6bfb5,0x3fffbfb5,
0x3f713fd5,0xbff53f8e,0xbfe23f8e,0x3f15bfd5,0xbf15bfed,0xbf713fed,0x3ff5bf44,0xbfe23f44,0x3e493ffb,0x3fc6bec8,0xbfff3ec8,0xbfa23ffb,
0x3ffb0000,0x3f8e0000,0xbec84000,0xbfd54000,0xbfd5bf44,0x3ffbbfed,0x3f8ebfed,0x3ec83f44,0x3f8e3fb5,0x3ec8bfb5,0xbfd53fb5,0x3ffbbfb5,
0xbec8bfed,0xbfd53f44,0x3ffbbf44,0x3f8ebfed,0xbfe23fb5,0xbff53fb5,0xbf71bfb5,0x3f15bfb5,0x3fffbec8,0xbfc63ffb,0xbe493ffb,0xbfa23ec8,
0xbfc6bf44,0x3e493f44,0x3fa2bfed,0xbfff3fed,0x3f153fd5,0x3fe2bf8e,0xbff53f8e,0xbf713fd5,0x3f44c000,0x3fedc000,0x3fed0000,0x3f440000,
0xbfed3fb5,0x3f44bfb5,0xbf44bfb5,0x3fedbfb5,0x3fed0000,0xbf440000,0xbf444000,0x3fedc000,0xbf44bfb5,0xbfed3fb5,0x3fedbfb5,0x3f44bfb5,
0x3f153fb5,0xbf713fb5,0xbff53fb5,0xbfe23fb5,0x3fa2bffb,0x3e493ec8,0x3fc63ec8,0xbfff3ffb,0xbfff3f44,0x3fa2bf44,0x3e49bfed,0xbfc63fed,
0x3f713f8e,0x3ff5bfd5,0xbfe23fd5,0xbf153f8e,0xbfd50000,0xbec80000,0x3f8ec000,0x3ffbc000,0xbec83fed,0xbf8e3f44,0xbffb3f44,0x3fd5bfed,
0x3ffbbfb5,0xbfd53fb5,0x3ec83fb5,0x3f8ebfb5,0xbf8ebf44,0xbffb3fed,0x3fd5bfed,0x3ec8bf44,0x3fffbfb5,0x3fc6bfb5,0x3e493fb5,0xbfa23fb5,
0xbf15bf8e,0x3fe2bfd5,0x3ff5bfd5,0xbf713f8e,0xbfe23fed,0x3ff5bfed,0xbf71bf44,0xbf153f44,0x3fa23ec8,0x3fffbffb,0xbfc63ffb,0xbe493ec8,
0xc0004000,0xbfb54000,0x0,0x3fb50000,0xc0004000,0x3fb50000,0x0,0x3fb5c000,0xc0004000,0x3fb5c000,0x0,0xbfb50000,
0xc0004000,0xbfb50000,0x0,0xbfb54000,0x3fc6bfb5,0x3fffbfb5,0x3fa2bfb5,0xbe49bfb5,0x3fe2bfd5,0xbf15bf8e,0x3f71bf8e,0xbff53fd5,
0x3ff5bfed,0xbfe23fed,0x3f15bf44,0x3f713f44,0x3fffbffb,0x3fa23ec8,0x3e49bec8,0x3fc6bffb,0xbec80000,0xbfd50000,0xbffb4000,0xbf8e4000,
0xbf8e3f44,0xbec83fed,0xbfd53fed,0x3ffbbf44,0xbfd53fb5,0x3ffbbfb5,0xbf8e3fb5,0xbec8bfb5,0xbffb3fed,0xbf8ebf44,0xbec83f44,0xbfd53fed,
0xbf713fb5,0x3f153fb5,0x3fe2bfb5,0x3ff5bfb5,0x3e493ec8,0x3fa2bffb,0x3fffbffb,0xbfc6bec8,0x3fa2bf44,0xbfff3f44,0x3fc6bfed,0xbe493fed,
0x3ff5bfd5,0x3f713f8e,0x3f15bf8e,0x3fe2bfd5,0x3fedc000,0x3f44c000,0xbf440000,0xbfed0000,0x3f44bfb5,0xbfed3fb5,0xbfed3fb5,0x3f443fb5,
0xbf440000,0x3fed0000,0xbfed4000,0x3f44c000,0xbfed3fb5,0xbf44bfb5,0xbf443fb5,0xbfed3fb5,0xbff53fb5,0xbfe23fb5,0xbf153fb5,0x3f713fb5,
0xbfc63ffb,0x3fffbec8,0x3fa2bec8,0x3e49bffb,0x3e493f44,0xbfc6bf44,0x3fffbfed,0xbfa23fed,0x3fe2bf8e,0x3f153fd5,0x3f71bfd5,0x3ff5bf8e,
0x3f8e0000,0x3ffb0000,0x3fd5c000,0x3ec8c000,0x3ffbbfed,0xbfd5bf44,0xbec8bf44,0xbf8e3fed,0x3ec8bfb5,0x3f8e3fb5,0xbffb3fb5,0x3fd5bfb5,
0xbfd53f44,0xbec8bfed,0xbf8e3fed,0xbffb3f44,0x3e49bfb5,0xbfa2bfb5,0xbfff3fb5,0xbfc63fb5,0xbff53f8e,0x3f713fd5,0xbf153fd5,0x3fe2bf8e,
0xbf713fed,0xbf15bfed,0x3fe2bf44,0xbff53f44,0x3fc6bec8,0x3e493ffb,0x3fa2bffb,0x3fffbec8,0x4000,0x3fb54000,0x40000000,0x3fb50000,
0xc000,0xbfb50000,0xc0000000,0x3fb54000,0x4000,0xbfb5c000,0x40000000,0xbfb50000,0xc000,0x3fb50000,0xc0000000,0xbfb5c000,
0x3fa2bfb5,0xbe49bfb5,0xbfc6bfb5,0xbfffbfb5,0xbf713fd5,0x3ff53f8e,0x3fe23f8e,0xbf15bfd5,0x3f15bfed,0x3f713fed,0xbff5bf44,0x3fe23f44,
0xbe493ffb,0xbfc6bec8,0x3fff3ec8,0x3fa23ffb,0xbffb0000,0xbf8e0000,0x3ec84000,0x3fd54000,0x3fd5bf44,0xbffbbfed,0xbf8ebfed,0xbec83f44,
0xbf8e3fb5,0xbec8bfb5,0x3fd53fb5,0xbffbbfb5,0x3ec8bfed,0x3fd53f44,0xbffbbf44,0xbf8ebfed,0x3fe23fb5,0x3ff53fb5,0x3f71bfb5,0xbf15bfb5,
0xbfffbec8,0x3fc63ffb,0x3e493ffb,0x3fa23ec8,0x3fc6bf44,0xbe493f44,0xbfa2bfed,0x3fff3fed,0xbf153fd5,0xbfe2bf8e,0x3ff53f8e,0x3f713fd5,
0xbf44c000,0xbfedc000,0xbfed0000,0xbf440000,0x3fed3fb5,0xbf44bfb5,0x3f44bfb5,0xbfedbfb5,0xbfed0000,0x3f440000,0x3f444000,0xbfedc000,
0x3f44bfb5,0x3fed3fb5,0xbfedbfb5,0xbf44bfb5,0xbf153fb5,0x3f713fb5,0x3ff53fb5,0x3fe23fb5,0xbfa2bffb,0xbe493ec8,0xbfc63ec8,0x3fff3ffb,
0x3fff3f44,0xbfa2bf44,0xbe49bfed,0x3fc63fed,0xbf713f8e,0xbff5bfd5,0x3fe23fd5,0x3f153f8e,0x3fd50000,0x3ec80000,0xbf8ec000,0xbffbc000,
0x3ec83fed,0x3f8e3f44,0x3ffb3f44,0xbfd5bfed,0xbffbbfb5,0x3fd53fb5,0xbec83fb5,0xbf8ebfb5,0x3f8ebf44,0x3ffb3fed,0xbfd5bfed,0xbec8bf44,
0xbfffbfb5,0xbfc6bfb5,0xbe493fb5,0x3fa23fb5,0x3f15bf8e,0xbfe2bfd5,0xbff5bfd5,0x3f713f8e,0x3fe23fed,0xbff5bfed,0x3f71bf44,0x3f153f44,
0xbfa23ec8,0xbfffbffb,0x3fc63ffb,0x3e493ec8,0x80003f80,0x3f800000,0x80003f80,0x3f800000,0x80003f80,0x3f800000,0x80003f80,0x3f800000,
0x80003f80,0x3f800000,0x80003f80,0x3f800000,0x80003f80,0x3f800000,0x80003f80,0x3f800000,0x80003f80,0x3f800000,0x8000bf80,0xbf800000,
0x3f353f35,0x3f35bf35,0xbf35bf35,0xbf353f35,0x3f800000,0xbf80,0xbf800000,0x3f80,0x3f35bf35,0xbf35bf35,0xbf353f35,0x3f353f35,
0x80003f80,0x3f800000,0x80003f80,0x3f800000,0x3f800000,0xbf80,0x3f800000,0xbf80,0x8000bf80,0xbf800000,0x8000bf80,0xbf800000,
0xbf800000,0x3f80,0xbf800000,0x3f80,0x80003f80,0x3f800000,0x8000bf80,0xbf800000,0x3f35bf35,0xbf35bf35,0xbf353f35,0x3f353f35,
0xbf800000,0x3f80,0x3f800000,0xbf80,0x3f353f35,0x3f35bf35,0xbf35bf35,0xbf353f35,0x80003f80,0x3f800000,0x80003f80,0x3f800000,
0x8000bf80,0xbf800000,0x8000bf80,0xbf800000,0x80003f80,0x3f800000,0x80003f80,0x3f800000,0x8000bf80,0xbf800000,0x8000bf80,0xbf800000,
0x80003f80,0x3f800000,0x8000bf80,0xbf800000,0xbf35bf35,0xbf353f35,0x3f353f35,0x3f35bf35,0x3f800000,0xbf80,0xbf800000,0x3f80,
0xbf353f35,0x3f353f35,0x3f35bf35,0xbf35bf35,0x80003f80,0x3f800000,0x80003f80,0x3f800000,0xbf800000,0x3f80,0xbf800000,0x3f80,
0x8000bf80,0xbf800000,0x8000bf80,0xbf800000,0x3f800000,0xbf80,0x3f800000,0xbf80,0x80003f80,0x3f800000,0x8000bf80,0xbf800000,
0xbf353f35,0x3f353f35,0x3f35bf35,0xbf35bf35,0xbf800000,0x3f80,0x3f800000,0xbf80,0xbf35bf35,0xbf353f35,0x3f353f35,0x3f35bf35,
0x3f803f80,0x80008000,0x80008000,0xbf80bf80,0x3f803f80,0x80008000,0x80008000,0xbf80bf80,0x3f803f80,0x80008000,0x80008000,0xbf80bf80,
0x3f803f80,0x80008000,0x80008000,0xbf80bf80,0x3f353f80,0x3f358000,0x3f358000,0xbf35bf80,0xbf350000,0x3f353f80,0x3f353f80,0x3f358000,
0xbf35bf80,0xbf358000,0xbf358000,0x3f353f80,0x3f350000,0xbf35bf80,0xbf35bf80,0xbf358000,0x3f80,0x3f808000,0x3f808000,0x8000bf80,
0xbf80,0xbf808000,0xbf808000,0x80003f80,0x3f80,0x3f808000,0x3f808000,0x8000bf80,0xbf80,0xbf808000,0xbf808000,0x80003f80,
0xbf353f80,0x3f358000,0x3f358000,0x3f35bf80,0x3f350000,0x3f35bf80,0x3f35bf80,0xbf358000,0x3f35bf80,0xbf358000,0xbf358000,0xbf353f80,
0xbf350000,0xbf353f80,0xbf353f80,0x3f358000,0xbf803f80,0x80008000,0x80008000,0x3f80bf80,0xbf803f80,0x80008000,0x80008000,0x3f80bf80,
0xbf803f80,0x80008000,0x80008000,0x3f80bf80,0xbf803f80,0x80008000,0x80008000,0x3f80bf80,0xbf353f80,0xbf358000,0xbf358000,0x3f35bf80,
0x3f350000,0xbf353f80,0xbf353f80,0xbf358000,0x3f35bf80,0x3f358000,0x3f358000,0xbf353f80,0xbf350000,0x3f35bf80,0x3f35bf80,0x3f358000,
0x3f80,0xbf808000,0xbf808000,0x8000bf80,0xbf80,0x3f808000,0x3f808000,0x80003f80,0x3f80,0xbf808000,0xbf808000,0x8000bf80,
0xbf80,0x3f808000,0x3f808000,0x80003f80,0x3f353f80,0xbf358000,0xbf358000,0xbf35bf80,0xbf350000,0xbf35bf80,0xbf35bf80,0x3f358000,
0xbf35bf80,0x3f358000,0x3f358000,0x3f353f80,0x3f350000,0x3f353f80,0x3f353f80,0xbf358000,0x3f800000,0x0,0x3f800000,0x0,
0x3f800000,0x0,0x3f800000,0x0,0x3f800000,0x0,0x3f800000,0x0,0x3f800000,0x0,0x3f800000,0x0,
0x3f800000,0x0,0x3f7fb10f,0xbd48fb30,0x3f7ec46d,0xbdc8bd36,0x3f7d3aac,0xbe164083,0x3f7b14be,0xbe47c5c2,0x3f7853f8,0xbe78cfcc,
0x3f74fa0b,0xbe94a031,0x3f710908,0xbeac7cd4,0x3f800000,0x0,0x3f7ec46d,0xbdc8bd36,0x3f7b14be,0xbe47c5c2,0x3f74fa0b,0xbe94a031,
0x3f6c835e,0xbec3ef15,0x3f61c598,0xbef15aea,0x3f54db31,0xbf0e39da,0x3f45e403,0xbf226799,0x3f800000,0x0,0x3f7d3aac,0xbe164083,
0x3f74fa0b,0xbe94a031,0x3f676bd8,0xbedae880,0x3f54db31,0xbf0e39da,0x3f3daef9,0xbf2beb4a,0x3f226799,0xbf45e403,0x3f039c3d,0xbf5b941a,
0x3f800000,0x0,0x3f7b14be,0xbe47c5c2,0x3f6c835e,0xbec3ef15,0x3f54db31,0xbf0e39da,0x3f3504f3,0xbf3504f3,0x3f0e39da,0xbf54db31,
0x3ec3ef15,0xbf6c835e,0x3e47c5c2,0xbf7b14be,0x3f800000,0x0,0x3f7853f8,0xbe78cfcc,0x3f61c598,0xbef15aea,0x3f3daef9,0xbf2beb4a,
0x3f0e39da,0xbf54db31,0x3eac7cd4,0xbf710908,0x3dc8bd36,0xbf7ec46d,0xbe164083,0xbf7d3aac,0x3f800000,0x0,0x3f74fa0b,0xbe94a031,
0x3f54db31,0xbf0e39da,0x3f226799,0xbf45e403,0x3ec3ef15,0xbf6c835e,0x3dc8bd36,0xbf7ec46d,0xbe47c5c2,0xbf7b14be,0xbef15aea,0xbf61c598,
0x3f800000,0x0,0x3f710908,0xbeac7cd4,0x3f45e403,0xbf226799,0x3f039c3d,0xbf5b941a,0x3e47c5c2,0xbf7b14be,0xbe164083,0xbf7d3aac,
0xbef15aea,0xbf61c598,0xbf3daef9,0xbf2beb4a,0x3f800000,0x0,0x3f800000,0x0,0x3f800000,0x0,0x3f800000,0x0,
0x3f800000,0x0,0x3f800000,0x0,0x3f800000,0x0,0x3f800000,0x0,0x3f6c835e,0xbec3ef15,0x3f676bd8,0xbedae880,
0x3f61c598,0xbef15aea,0x3f5b941a,0xbf039c3d,0x3f54db31,0xbf0e39da,0x3f4d9f02,0xbf187fc0,0x3f45e403,0xbf226799,0x3f3daef9,0xbf2beb4a,
0x3f3504f3,0xbf3504f3,0x3f226799,0xbf45e403,0x3f0e39da,0xbf54db31,0x3ef15aea,0xbf61c598,0x3ec3ef15,0xbf6c835e,0x3e94a031,0xbf74fa0b,
0x3e47c5c2,0xbf7b14be,0x3dc8bd36,0xbf7ec46d,0x3ec3ef15,0xbf6c835e,0x3e78cfcc,0xbf7853f8,0x3dc8bd36,0xbf7ec46d,0xbd48fb30,0xbf7fb10f,
0xbe47c5c2,0xbf7b14be,0xbeac7cd4,0xbf710908,0xbef15aea,0xbf61c598,0xbf187fc0,0xbf4d9f02,0x0,0xbf800000,0xbe47c5c2,0xbf7b14be,
0xbec3ef15,0xbf6c835e,0xbf0e39da,0xbf54db31,0xbf3504f3,0xbf3504f3,0xbf54db31,0xbf0e39da,0xbf6c835e,0xbec3ef15,0xbf7b14be,0xbe47c5c2,
0xbec3ef15,0xbf6c835e,0xbf187fc0,0xbf4d9f02,0xbf45e403,0xbf226799,0xbf676bd8,0xbedae880,0xbf7b14be,0xbe47c5c2,0xbf7fb10f,0x3d48fb30,
0xbf74fa0b,0x3e94a031,0xbf5b941a,0x3f039c3d,0xbf3504f3,0xbf3504f3,0xbf61c598,0xbef15aea,0xbf7b14be,0xbe47c5c2,0xbf7ec46d,0x3dc8bd36,
0xbf6c835e,0x3ec3ef15,0xbf45e403,0x3f226799,0xbf0e39da,0x3f54db31,0xbe94a031,0x3f74fa0b,0xbf6c835e,0xbec3ef15,0xbf7fb10f,0xbd48fb30,
0xbf74fa0b,0x3e94a031,0xbf4d9f02,0x3f187fc0,0xbf0e39da,0x3f54db31,0xbe78cfcc,0x3f7853f8,0x3dc8bd36,0x3f7ec46d,0x3edae880,0x3f676bd8,
0x80003f80,0x3f800000,0x3f800000,0xbf80,0x3ec43f6d,0x3f6dbec4,0x3f6dbec4,0xbec4bf6d,0x3f353f35,0x3f35bf35,0x3f35bf35,0xbf35bf35,
0x3f6d3ec4,0x3ec4bf6d,0x3ec4bf6d,0xbf6dbec4,0x80003f80,0x3f800000,0xbf800000,0x3f80,0x3f6d3ec4,0x3ec4bf6d,0xbec43f6d,0x3f6d3ec4,
0x3f35bf35,0xbf35bf35,0x3f353f35,0x3f35bf35,0xbec4bf6d,0xbf6d3ec4,0x3f6dbec4,0xbec4bf6d,0x80003f80,0x3f800000,0x3f800000,0xbf80,
0x3f6dbec4,0xbec4bf6d,0xbec4bf6d,0xbf6d3ec4,0xbf35bf35,0xbf353f35,0xbf353f35,0x3f353f35,0xbec43f6d,0x3f6d3ec4,0x3f6d3ec4,0x3ec4bf6d,
0x80003f80,0x3f800000,0xbf800000,0x3f80,0x3ec4bf6d,0xbf6dbec4,0x3f6d3ec4,0x3ec4bf6d,0xbf353f35,0x3f353f35,0xbf35bf35,0xbf353f35,
0x3f6dbec4,0xbec4bf6d,0x3ec43f6d,0x3f6dbec4,0x80003f80,0x3f800000,0x3f800000,0xbf80,0xbec4bf6d,0xbf6d3ec4,0xbf6d3ec4,0x3ec43f6d,
0x3f353f35,0x3f35bf35,0x3f35bf35,0xbf35bf35,0xbf6dbec4,0xbec43f6d,0xbec43f6d,0x3f6d3ec4,0x80003f80,0x3f800000,0xbf800000,0x3f80,
0xbf6dbec4,0xbec43f6d,0x3ec4bf6d,0xbf6dbec4,0x3f35bf35,0xbf35bf35,0x3f353f35,0x3f35bf35,0x3ec43f6d,0x3f6dbec4,0xbf6d3ec4,0x3ec43f6d,
0x80003f80,0x3f800000,0x3f800000,0xbf80,0xbf6d3ec4,0x3ec43f6d,0x3ec43f6d,0x3f6dbec4,0xbf35bf35,0xbf353f35,0xbf353f35,0x3f353f35,
0x3ec4bf6d,0xbf6dbec4,0xbf6dbec4,0xbec43f6d,0x80003f80,0x3f800000,0xbf800000,0x3f80,0xbec43f6d,0x3f6d3ec4,0xbf6dbec4,0xbec43f6d,
0xbf353f35,0x3f353f35,0xbf35bf35,0xbf353f35,0xbf6d3ec4,0x3ec43f6d,0xbec4bf6d,0xbf6d3ec4,0x3f803f80,0x80008000,0x80008000,0xbf80bf80,
0x3f803f80,0x80008000,0x80008000,0xbf80bf80,0x3f803f80,0x80008000,0x80008000,0xbf80bf80,0x3f803f80,0x80008000,0x80008000,0xbf80bf80,
0x3ec43f6d,0x3f6d3ec4,0x3f6d3ec4,0xbec4bf6d,0xbf6dbec4,0x3ec43f6d,0x3ec43f6d,0x3f6d3ec4,0xbec4bf6d,0xbf6dbec4,0xbf6dbec4,0x3ec43f6d,
0x3f6d3ec4,0xbec4bf6d,0xbec4bf6d,0xbf6dbec4,0xbf353f35,0x3f353f35,0x3f353f35,0x3f35bf35,0x3f35bf35,0xbf35bf35,0xbf35bf35,0xbf353f35,
0xbf353f35,0x3f353f35,0x3f353f35,0x3f35bf35,0x3f35bf35,0xbf35bf35,0xbf35bf35,0xbf353f35,0xbf6d3ec4,0xbec43f6d,0xbec43f6d,0x3f6dbec4,
0xbec43f6d,0x3f6dbec4,0x3f6dbec4,0x3ec4bf6d,0x3f6dbec4,0x3ec4bf6d,0x3ec4bf6d,0xbf6d3ec4,0x3ec4bf6d,0xbf6d3ec4,0xbf6d3ec4,0xbec43f6d,
0x0,0xbf803f80,0xbf803f80,0x80008000,0x0,0xbf803f80,0xbf803f80,0x80008000,0x0,0xbf803f80,0xbf803f80,0x80008000,
0x0,0xbf803f80,0xbf803f80,0x80008000,0x3f6dbec4,0xbec43f6d,0xbec43f6d,0xbf6d3ec4,0x3ec4bf6d,0x3f6dbec4,0x3f6dbec4,0xbec43f6d,
0xbf6d3ec4,0x3ec4bf6d,0x3ec4bf6d,0x3f6dbec4,0xbec43f6d,0xbf6d3ec4,0xbf6d3ec4,0x3ec4bf6d,0x3f35bf35,0x3f353f35,0x3f353f35,0xbf353f35,
0xbf353f35,0xbf35bf35,0xbf35bf35,0x3f35bf35,0x3f35bf35,0x3f353f35,0x3f353f35,0xbf353f35,0xbf353f35,0xbf35bf35,0xbf35bf35,0x3f35bf35,
0xbec4bf6d,0x3f6d3ec4,0x3f6d3ec4,0x3ec43f6d,0x3f6d3ec4,0x3ec43f6d,0x3ec43f6d,0xbf6dbec4,0x3ec43f6d,0xbf6dbec4,0xbf6dbec4,0xbec4bf6d,
0xbf6dbec4,0xbec4bf6d,0xbec4bf6d,0x3f6d3ec4,0x3f800000,0x0,0x3f7fec43,0xbcc90ab0,0x3f7fb10f,0xbd48fb30,0x3f7f4e6d,0xbd96a905,
0x3f7ec46d,0xbdc8bd36,0x3f7e1324,0xbdfab273,0x3f7d3aac,0xbe164083,0x3f7c3b28,0xbe2f10a2,0x3f800000,0x0,0x3f7f4e6d,0xbd96a905,
0x3f7d3aac,0xbe164083,0x3f79c79d,0xbe605c13,0x3f74fa0b,0xbe94a031,0x3f6ed89e,0xbeb8442a,0x3f676bd8,0xbedae880,0x3f5ebe05,0xbefc5d27,
0x3f800000,0x0,0x3f7e1324,0xbdfab273,0x3f7853f8,0xbe78cfcc,0x3f6ed89e,0xbeb8442a,0x3f61c598,0xbef15aea,0x3f514d3d,0xbf13682a,
0x3f3daef9,0xbf2beb4a,0x3f273656,0xbf41d870,0x3f800000,0x0,0x3f7c3b28,0xbe2f10a2,0x3f710908,0xbeac7cd4,0x3f5ebe05,0xbefc5d27,
0x3f45e403,0xbf226799,0x3f273656,0xbf41d870,0x3f039c3d,0xbf5b941a,0x3eb8442a,0xbf6ed89e,0x3f800000,0x0,0x3f79c79d,0xbe605c13,
0x3f676bd8,0xbedae880,0x3f49d112,0xbf1d7fd1,0x3f226799,0xbf45e403,0x3ee63375,0xbf64aa59,0x3e78cfcc,0xbf7853f8,0x3cc90ab0,0xbf7fec43,
0x3f800000,0x0,0x3f76ba07,0xbe888e93,0x3f5b941a,0xbf039c3d,0x3f3085bb,0xbf396842,0x3ef15aea,0xbf61c598,0x3e605c13,0xbf79c79d,
0xbd48fb30,0xbf7fb10f,0xbea09ae5,0xbf731447,0x3f800000,0x0,0x3f731447,0xbea09ae5,0x3f4d9f02,0xbf187fc0,0x3f13682a,0xbf514d3d,
0x3e94a031,0xbf74fa0b,0xbcc90ab0,0xbf7fec43,0xbeac7cd4,0xbf710908,0xbf1d7fd1,0xbf49d112,0x3f800000,0x0,0x3f6ed89e,0xbeb8442a,
0x3f3daef9,0xbf2beb4a,0x3ee63375,0xbf64aa59,0x3dc8bd36,0xbf7ec46d,0xbe888e93,0xbf76ba07,0xbf187fc0,0xbf4d9f02,0xbf584853,0xbf08f59b,
0x3f7b14be,0xbe47c5c2,0x3f79c79d,0xbe605c13,0x3f7853f8,0xbe78cfcc,0x3f76ba07,0xbe888e93,0x3f74fa0b,0xbe94a031,0x3f731447,0xbea09ae5,
0x3f710908,0xbeac7cd4,0x3f6ed89e,0xbeb8442a,0x3f54db31,0xbf0e39da,0x3f49d112,0xbf1d7fd1,0x3f3daef9,0xbf2beb4a,0x3f3085bb,0xbf396842,
0x3f226799,0xbf45e403,0x3f13682a,0xbf514d3d,0x3f039c3d,0xbf5b941a,0x3ee63375,0xbf64aa59,0x3f0e39da,0xbf54db31,0x3ee63375,0xbf64aa59,
0x3eac7cd4,0xbf710908,0x3e605c13,0xbf79c79d,0x3dc8bd36,0xbf7ec46d,0xbcc90ab0,0xbf7fec43,0xbe164083,0xbf7d3aac,0xbe888e93,0xbf76ba07,
0x3e47c5c2,0xbf7b14be,0x3cc90ab0,0xbf7fec43,0xbe164083,0xbf7d3aac,0xbea09ae5,0xbf731447,0xbef15aea,0xbf61c598,0xbf1d7fd1,0xbf49d112,
0xbf3daef9,0xbf2beb4a,0xbf584853,0xbf08f59b,0xbe47c5c2,0xbf7b14be,0xbecf7bca,0xbf6a09a7,0xbf187fc0,0xbf4d9f02,0xbf41d870,0xbf273656,
0xbf61c598,0xbef15aea,0xbf76ba07,0xbe888e93,0xbf7fb10f,0xbd48fb30,0xbf7c3b28,0x3e2f10a2,0xbf0e39da,0xbf54db31,0xbf41d870,0xbf273656,
0xbf676bd8,0xbedae880,0xbf7c3b28,0xbe2f10a2,0xbf7ec46d,0x3dc8bd36,0xbf6ed89e,0x3eb8442a,0xbf4d9f02,0x3f187fc0,0xbf1d7fd1,0x3f49d112,
0xbf54db31,0xbf0e39da,0xbf76ba07,0xbe888e93,0xbf7fb10f,0x3d48fb30,0xbf6ed89e,0x3eb8442a,0xbf45e403,0x3f226799,0xbf08f59b,0x3f584853,
0xbe78cfcc,0x3f7853f8,0x3d96a905,0x3f7f4e6d,0xbf7b14be,0xbe47c5c2,0xbf7c3b28,0x3e2f10a2,0xbf5b941a,0x3f039c3d,0xbf1d7fd1,0x3f49d112,
0xbe94a031,0x3f74fa0b,0x3d96a905,0x3f7f4e6d,0x3edae880,0x3f676bd8,0x3f396842,0x3f3085bb,0x80003f80,0x80003f80,0x80003f80,0x80003f80,
0x80003f80,0x80003f80,0x80003f80,0x80003f80,0x80003f80,0x80003f80,0x80003f80,0x80003f80,0x80003f80,0x80003f80,0x80003f80,0x80003f80,
0x3f800000,0x3f800000,0x3f800000,0x3f800000,0x3f800000,0x3f800000,0x3f800000,0x3f800000,0x3f800000,0x3f800000,0x3f800000,0x3f800000,
0x3f800000,0x3f800000,0x3f800000,0x3f800000,0x80003f80,0x3f353f35,0x80003f80,0x3f353f35,0x3f800000,0x3f35bf35,0x3f800000,0x3f35bf35,
0x8000bf80,0xbf35bf35,0x8000bf80,0xbf35bf35,0xbf800000,0xbf353f35,0xbf800000,0xbf353f35,0x3f800000,0x3f35bf35,0x3f800000,0x3f35bf35,
0xbf80,0xbf35bf35,0xbf80,0xbf35bf35,0xbf800000,0xbf353f35,0xbf800000,0xbf353f35,0x3f80,0x3f353f35,0x3f80,0x3f353f35,
0x80003f80,0x3f800000,0x80003f80,0x3f800000,0x8000bf80,0xbf800000,0x8000bf80,0xbf800000,0x80003f80,0x3f800000,0x80003f80,0x3f800000,
0x8000bf80,0xbf800000,0x8000bf80,0xbf800000,0x3f800000,0xbf80,0x3f800000,0xbf80,0xbf800000,0x3f80,0xbf800000,0x3f80,
0x3f800000,0xbf80,0x3f800000,0xbf80,0xbf800000,0x3f80,0xbf800000,0x3f80,0x80003f80,0x3f35bf35,0x80003f80,0x3f35bf35,
0xbf800000,0x3f353f35,0xbf800000,0x3f353f35,0x8000bf80,0xbf353f35,0x8000bf80,0xbf353f35,0x3f800000,0xbf35bf35,0x3f800000,0xbf35bf35,
0x3f800000,0xbf35bf35,0x3f800000,0xbf35bf35,0x3f80,0x3f35bf35,0x3f80,0x3f35bf35,0xbf800000,0x3f353f35,0xbf800000,0x3f353f35,
0xbf80,0xbf353f35,0xbf80,0xbf353f35,0x80003f80,0x3ec43f6d,0x8000bf80,0xbec4bf6d,0x3f353f35,0x3f6d3ec4,0xbf35bf35,0xbf6dbec4,
0x3f800000,0x3f6dbec4,0xbf800000,0xbf6d3ec4,0x3f35bf35,0x3ec4bf6d,0xbf353f35,0xbec43f6d,0x3f800000,0x3f6dbec4,0xbf800000,0xbf6d3ec4,
0x3f35bf35,0x3ec4bf6d,0xbf353f35,0xbec43f6d,0xbf80,0xbec4bf6d,0x3f80,0x3ec43f6d,0xbf35bf35,0xbf6dbec4,0x3f353f35,0x3f6d3ec4,
0x80003f80,0x3f6d3ec4,0x8000bf80,0xbf6dbec4,0x3f35bf35,0xbec4bf6d,0xbf353f35,0x3ec43f6d,0xbf800000,0xbec43f6d,0x3f800000,0x3ec4bf6d,
0x3f353f35,0x3f6dbec4,0xbf35bf35,0xbf6d3ec4,0x3f800000,0x3ec4bf6d,0xbf800000,0xbec43f6d,0xbf35bf35,0xbf6d3ec4,0x3f353f35,0x3f6dbec4,
0x3f80,0x3f6d3ec4,0xbf80,0xbf6dbec4,0x3f35bf35,0xbec4bf6d,0xbf353f35,0x3ec43f6d,0x80003f80,0x3f6dbec4,0x8000bf80,0xbf6d3ec4,
0xbf35bf35,0xbec43f6d,0x3f353f35,0x3ec4bf6d,0x3f800000,0xbec4bf6d,0xbf800000,0x3ec43f6d,0xbf353f35,0x3f6d3ec4,0x3f35bf35,0xbf6dbec4,
0x3f800000,0xbec4bf6d,0xbf800000,0x3ec43f6d,0xbf353f35,0x3f6d3ec4,0x3f35bf35,0xbf6dbec4,0xbf80,0xbf6d3ec4,0x3f80,0x3f6dbec4,
0x3f353f35,0x3ec4bf6d,0xbf35bf35,0xbec43f6d,0x80003f80,0x3ec4bf6d,0x8000bf80,0xbec43f6d,0xbf353f35,0x3f6dbec4,0x3f35bf35,0xbf6d3ec4,
0xbf800000,0x3f6d3ec4,0x3f800000,0xbf6dbec4,0xbf35bf35,0x3ec43f6d,0x3f353f35,0xbec4bf6d,0x3f800000,0xbf6dbec4,0xbf800000,0x3f6d3ec4,
0x3f353f35,0xbec4bf6d,0xbf35bf35,0x3ec43f6d,0x3f80,0x3ec4bf6d,0xbf80,0xbec43f6d,0xbf353f35,0x3f6dbec4,0x3f35bf35,0xbf6d3ec4,
0x80003f80,0x8000bf80,0x80003f80,0x8000bf80,0x80003f80,0x8000bf80,0x80003f80,0x8000bf80,0x80003f80,0x8000bf80,0x80003f80,0x8000bf80,
0x80003f80,0x8000bf80,0x80003f80,0x8000bf80,0x3f800000,0xbf800000,0x3f800000,0xbf800000,0x3f800000,0xbf800000,0x3f800000,0xbf800000,
0x3f800000,0xbf800000,0x3f800000,0xbf800000,0x3f800000,0xbf800000,0x3f800000,0xbf800000,0x80003f80,0xbf35bf35,0x80003f80,0xbf35bf35,
0x3f800000,0xbf353f35,0x3f800000,0xbf353f35,0x8000bf80,0x3f353f35,0x8000bf80,0x3f353f35,0xbf800000,0x3f35bf35,0xbf800000,0x3f35bf35,
0x3f800000,0xbf353f35,0x3f800000,0xbf353f35,0xbf80,0x3f353f35,0xbf80,0x3f353f35,0xbf800000,0x3f35bf35,0xbf800000,0x3f35bf35,
0x3f80,0xbf35bf35,0x3f80,0xbf35bf35,0x80003f80,0xbf800000,0x80003f80,0xbf800000,0x8000bf80,0x3f800000,0x8000bf80,0x3f800000,
0x80003f80,0xbf800000,0x80003f80,0xbf800000,0x8000bf80,0x3f800000,0x8000bf80,0x3f800000,0x3f800000,0x3f80,0x3f800000,0x3f80,
0xbf800000,0xbf80,0xbf800000,0xbf80,0x3f800000,0x3f80,0x3f800000,0x3f80,0xbf800000,0xbf80,0xbf800000,0xbf80,
0x80003f80,0xbf353f35,0x80003f80,0xbf353f35,0xbf800000,0xbf35bf35,0xbf800000,0xbf35bf35,0x8000bf80,0x3f35bf35,0x8000bf80,0x3f35bf35,
0x3f800000,0x3f353f35,0x3f800000,0x3f353f35,0x3f800000,0x3f353f35,0x3f800000,0x3f353f35,0x3f80,0xbf353f35,0x3f80,0xbf353f35,
0xbf800000,0xbf35bf35,0xbf800000,0xbf35bf35,0xbf80,0x3f35bf35,0xbf80,0x3f35bf35,0x80003f80,0xbec4bf6d,0x8000bf80,0x3ec43f6d,
0x3f353f35,0xbf6dbec4,0xbf35bf35,0x3f6d3ec4,0x3f800000,0xbf6d3ec4,0xbf800000,0x3f6dbec4,0x3f35bf35,0xbec43f6d,0xbf353f35,0x3ec4bf6d,
0x3f800000,0xbf6d3ec4,0xbf800000,0x3f6dbec4,0x3f35bf35,0xbec43f6d,0xbf353f35,0x3ec4bf6d,0xbf80,0x3ec43f6d,0x3f80,0xbec4bf6d,
0xbf35bf35,0x3f6d3ec4,0x3f353f35,0xbf6dbec4,0x80003f80,0xbf6dbec4,0x8000bf80,0x3f6d3ec4,0x3f35bf35,0x3ec43f6d,0xbf353f35,0xbec4bf6d,
0xbf800000,0x3ec4bf6d,0x3f800000,0xbec43f6d,0x3f353f35,0xbf6d3ec4,0xbf35bf35,0x3f6dbec4,0x3f800000,0xbec43f6d,0xbf800000,0x3ec4bf6d,
0xbf35bf35,0x3f6dbec4,0x3f353f35,0xbf6d3ec4,0x3f80,0xbf6dbec4,0xbf80,0x3f6d3ec4,0x3f35bf35,0x3ec43f6d,0xbf353f35,0xbec4bf6d,
0x80003f80,0xbf6d3ec4,0x8000bf80,0x3f6dbec4,0xbf35bf35,0x3ec4bf6d,0x3f353f35,0xbec43f6d,0x3f800000,0x3ec43f6d,0xbf800000,0xbec4bf6d,
0xbf353f35,0xbf6dbec4,0x3f35bf35,0x3f6d3ec4,0x3f800000,0x3ec43f6d,0xbf800000,0xbec4bf6d,0xbf353f35,0xbf6dbec4,0x3f35bf35,0x3f6d3ec4,
0xbf80,0x3f6dbec4,0x3f80,0xbf6d3ec4,0x3f353f35,0xbec43f6d,0xbf35bf35,0x3ec4bf6d,0x80003f80,0xbec43f6d,0x8000bf80,0x3ec4bf6d,
0xbf353f35,0xbf6d3ec4,0x3f35bf35,0x3f6dbec4,0xbf800000,0xbf6dbec4,0x3f800000,0x3f6d3ec4,0xbf35bf35,0xbec4bf6d,0x3f353f35,0x3ec43f6d,
0x3f800000,0x3f6d3ec4,0xbf800000,0xbf6dbec4,0x3f353f35,0x3ec43f6d,0xbf35bf35,0xbec4bf6d,0x3f80,0xbec43f6d,0xbf80,0x3ec4bf6d,
0xbf353f35,0xbf6d3ec4,0x3f35bf35,0x3f6dbec4,
};
constexpr int TB_F = 0, TB_E = 512, TB_P2 = 1024;

enum { C_EP = 0, C_Z1 = 32, C_Z2 = 96, C_H3 = 128, C_U = 160, C_X = 288, C_TOTAL = 512 };
struct Scratch {
  unsigned cnt[C_TOTAL];
  uint32_t moda[8 * 2 * D_];
  uint32_t mod[4 * D_ + 256];
  uint32_t z1[120 * 5120];
  uint32_t z2[128 * 4800];
  uint8_t h3[32 * 18 * 4096];
  uint8_t u[72 * D_ * 128];
};
__device__ __align__(1024) Scratch g_s;

#define PF2 8
#define PF2K 16
#define HOLDA 5
#define GOAT 0
#define H3W 0
#define X1K 10
#define PEEK 1
#ifndef NV1
#define NV1 12
#endif
#ifndef NV2
#define NV2 20
#endif
#define GDEP 0
#define TRK0 50
#define W0N 3
#define TRKC 350
#define J2 6
#define MODPOS 2
#define LNM 0x30
constexpr int NB15 = 192 + 32 * __builtin_popcount(LNM);
#define NG1 2

#define FAILCNT(k) do {} while (0)
#define CK(k) do {} while (0)
#define CKX(k) do {} while (0)
#define TS(k) do {} while (0)
#define TSC(k) do {} while (0)
struct Maps { CUtensorMap z1, z2[2], w1a, w1b, h3, w2, wf[4], wm; };
struct Params {
  const __nv_bfloat16 *x, *c, *wmod;
  Scratch* s;
  const uint4* tab;
  const __nv_bfloat16 *wr, *wi, *w1, *w2, *b1, *b2;
  uint32_t* out;
};

__device__ __forceinline__ uint32_t smem_u32(const void* p) { return (uint32_t)__cvta_generic_to_shared(p); }
__device__ __forceinline__ void mbar_init(uint32_t b, int c) { asm volatile("mbarrier.init.shared::cta.b64 [%0], %1;" ::"r"(b), "r"(c)); }
__device__ __forceinline__ void mbar_expect(uint32_t b, int bytes) { asm volatile("mbarrier.arrive.expect_tx.shared::cta.b64 _, [%0], %1;" ::"r"(b), "r"(bytes) : "memory"); }
__device__ __forceinline__ void mbar_arrive(uint32_t b) { asm volatile("mbarrier.arrive.shared::cta.b64 _, [%0];" ::"r"(b) : "memory"); }
#define MBAR_WAIT(SEM)                                                                                                         \
  asm volatile("{\n.reg .pred p;\n.reg .u32 it;\nmov.u32 it, 0;\nW:\nmbarrier.try_wait.parity" SEM ".shared::cta.b64 p, [%0], %1;\n" \
               "@p bra.uni D;\nadd.u32 it, it, 1;\nsetp.lt.u32 p, it, 0x400000;\n@p bra.uni W;\ntrap;\nD:\n}" ::"r"(b), "r"(ph) : "memory")
__device__ __forceinline__ void mbar_wait(uint32_t b, int ph) { MBAR_WAIT(""); }
__device__ __forceinline__ uint32_t mbar_test(uint32_t b, int ph) {
  uint32_t ok;
  asm volatile("{\n.reg .pred p;\nmbarrier.test_wait.parity.shared::cta.b64 p, [%1], %2;\nselp.u32 %0, 1, 0, p;\n}\n" : "=r"(ok) : "r"(b), "r"(ph) : "memory");
  return ok;
}
__device__ __forceinline__ void tma2d(uint32_t dst, const CUtensorMap* m, int c0, int c1, uint32_t bar) {
  asm volatile("cp.async.bulk.tensor.2d.shared::cluster.global.mbarrier::complete_tx::bytes [%0], [%1, {%3, %4}], [%2];" ::"r"(dst), "l"(m), "r"(bar), "r"(c0), "r"(c1) : "memory");
}
__device__ __forceinline__ uint64_t pol_ef() { uint64_t p; asm("createpolicy.fractional.L2::evict_first.b64 %0, 1.0;" : "=l"(p)); return p; }
__device__ __forceinline__ void tma3d_ef(uint32_t dst, const CUtensorMap* m, int c1, int c2, uint32_t bar) {
  asm volatile("cp.async.bulk.tensor.3d.shared::cluster.global.mbarrier::complete_tx::bytes.L2::cache_hint [%0], [%1, {%3, %4, %5}], [%2], %6;" ::"r"(dst), "l"(m), "r"(bar), "r"(0), "r"(c1), "r"(c2), "l"(pol_ef()) : "memory");
}
__device__ __forceinline__ void tma4d_ef(uint32_t dst, const CUtensorMap* m, int c1, int c2, int c3, uint32_t bar) {
  asm volatile("cp.async.bulk.tensor.4d.shared::cluster.global.mbarrier::complete_tx::bytes.L2::cache_hint [%0], [%1, {%3, %7, %4, %5}], [%2], %6;" ::"r"(dst), "l"(m), "r"(bar), "r"(0), "r"(c2), "r"(c3), "l"(pol_ef()), "r"(c1) : "memory");
}
__device__ __forceinline__ void bulk_ld(uint32_t dst, const void* src, int bytes, uint32_t bar) {
  asm volatile("cp.async.bulk.shared::cluster.global.mbarrier::complete_tx::bytes [%0], [%1], %2, [%3];" ::"r"(dst), "l"(src), "r"(bytes), "r"(bar) : "memory");
}
__device__ __forceinline__ void bulk_st(void* dst, uint32_t src, int bytes) {
  asm volatile("cp.async.bulk.global.shared::cta.bulk_group [%0], [%1], %2;" ::"l"(dst), "r"(src), "r"(bytes) : "memory");
}
__device__ __forceinline__ void tma_st2d(const CUtensorMap* m, uint32_t src, int c0, int c1) {
  asm volatile("cp.async.bulk.tensor.2d.global.shared::cta.bulk_group [%0, {%2, %3}], [%1];" ::"l"(m), "r"(src), "r"(c0), "r"(c1) : "memory");
}
__device__ __forceinline__ void tma_st3d(const CUtensorMap* m, uint32_t src, int c0, int c1, int c2) {
  asm volatile("cp.async.bulk.tensor.3d.global.shared::cta.bulk_group [%0, {%2, %3, %4}], [%1];" ::"l"(m), "r"(src), "r"(c0), "r"(c1), "r"(c2) : "memory");
}
__device__ __forceinline__ void bulk_commit_wait_read() {
  asm volatile("cp.async.bulk.commit_group;" ::: "memory");
  asm volatile("cp.async.bulk.wait_group.read 0;" ::: "memory");
}
__device__ __forceinline__ void bulk_commit_wait() {
  asm volatile("cp.async.bulk.commit_group;" ::: "memory");
  asm volatile("cp.async.bulk.wait_group 0;" ::: "memory");
}
__device__ __forceinline__ void prefetch_l2(const void* p, int bytes) {
  asm volatile("cp.async.bulk.prefetch.L2.global [%0], %1;" ::"l"(p), "r"(bytes) : "memory");
}
__device__ __forceinline__ void wg_fence() { asm volatile("wgmma.fence.sync.aligned;" ::: "memory"); }
__device__ __forceinline__ void wg_commit() { asm volatile("wgmma.commit_group.sync.aligned;" ::: "memory"); }
template <int N> __device__ __forceinline__ void wg_wait() { asm volatile("wgmma.wait_group.sync.aligned %0;" ::"n"(N) : "memory"); }
template <int N> __device__ __forceinline__ void reg_fence(float (&d)[N]) {
#pragma unroll
  for (int i = 0; i < N; i++) asm volatile("" : "+f"(d[i])::"memory");
}
__device__ __forceinline__ void fence_async_smem() { asm volatile("fence.proxy.async.shared::cta;" ::: "memory"); }
__device__ __forceinline__ void fence_async_glb() { asm volatile("fence.proxy.async.global;" ::: "memory"); }
__device__ __forceinline__ uint32_t ld_rlx(const void* p) { uint32_t v; asm volatile("ld.relaxed.gpu.global.b32 %0, [%1];" : "=r"(v) : "l"(p) : "memory"); return v; }
__device__ __forceinline__ uint2 ld_rlx2(const void* p) { uint2 v; asm volatile("ld.relaxed.gpu.global.v2.b32 {%0,%1}, [%2];" : "=r"(v.x), "=r"(v.y) : "l"(p) : "memory"); return v; }
__device__ __forceinline__ uint4 ld_rlx4(const void* p) { uint4 v; asm volatile("ld.relaxed.gpu.global.v4.b32 {%0,%1,%2,%3}, [%4];" : "=r"(v.x), "=r"(v.y), "=r"(v.z), "=r"(v.w) : "l"(p) : "memory"); return v; }
__device__ __forceinline__ uint32_t ld_nc(const void* p) { uint32_t v; asm volatile("ld.global.nc.L1::no_allocate.b32 %0, [%1];" : "=r"(v) : "l"(p) : "memory"); return v; }
__device__ __forceinline__ uint4 ld_nc4(const void* p) { uint4 v; asm volatile("ld.global.nc.v4.b32 {%0,%1,%2,%3}, [%4];" : "=r"(v.x), "=r"(v.y), "=r"(v.z), "=r"(v.w) : "l"(p) : "memory"); return v; }
__device__ __forceinline__ uint32_t lds(uint32_t a) { uint32_t v; asm volatile("ld.shared.b32 %0, [%1];" : "=r"(v) : "r"(a) : "memory"); return v; }
__device__ __forceinline__ uint2 lds2(uint32_t a) { uint2 v; asm volatile("ld.shared.v2.b32 {%0,%1}, [%2];" : "=r"(v.x), "=r"(v.y) : "r"(a) : "memory"); return v; }
__device__ __forceinline__ uint4 lds4(uint32_t a) { uint4 v; asm volatile("ld.shared.v4.b32 {%0,%1,%2,%3}, [%4];" : "=r"(v.x), "=r"(v.y), "=r"(v.z), "=r"(v.w) : "r"(a) : "memory"); return v; }
__device__ __forceinline__ float lds_bf(uint32_t a) { uint32_t v; asm volatile("ld.shared.u16 %0, [%1];" : "=r"(v) : "r"(a) : "memory"); return __uint_as_float(v << 16); }
__device__ __forceinline__ void sts(uint32_t a, uint32_t v) { asm volatile("st.shared.b32 [%0], %1;" ::"r"(a), "r"(v) : "memory"); }
__device__ __forceinline__ void sts2(uint32_t a, uint32_t v0, uint32_t v1) { asm volatile("st.shared.v2.b32 [%0], {%1,%2};" ::"r"(a), "r"(v0), "r"(v1) : "memory"); }
__device__ __forceinline__ void sts4(uint32_t a, uint32_t v0, uint32_t v1, uint32_t v2, uint32_t v3) { asm volatile("st.shared.v4.b32 [%0], {%1,%2,%3,%4};" ::"r"(a), "r"(v0), "r"(v1), "r"(v2), "r"(v3) : "memory"); }
__device__ __forceinline__ void bar_sync(int id, int n) { asm volatile("bar.sync %0, %1;" ::"r"(id), "r"(n) : "memory"); }
__device__ __forceinline__ void bar_arrive(int id, int n) { asm volatile("bar.arrive %0, %1;" ::"r"(id), "r"(n) : "memory"); }
__device__ __forceinline__ void red_add(unsigned* p, unsigned v) { asm volatile("red.relaxed.gpu.global.add.u32 [%0], %1;" ::"l"(p), "r"(v) : "memory"); }
__device__ __forceinline__ bool any(bool p) { return __any_sync(0xffffffffu, p); }
__device__ __forceinline__ void pause(unsigned clks) {
  asm volatile("{\n.reg .pred p;\n.reg .u32 a, b;\nmov.u32 a, %%clock;\nW:\nmov.u32 b, %%clock;\nsub.u32 b, b, a;\nsetp.lt.s32 p, b, %0;\n@p bra.uni W;\n}" ::"r"(clks) : "memory");
}
__device__ __forceinline__ void red_bf16x8(uint32_t* p, uint32_t a, uint32_t b, uint32_t c, uint32_t d) {
  asm volatile("red.relaxed.gpu.global.add.noftz.v4.bf16x2 [%0], {%1,%2,%3,%4};" ::"l"(p), "r"(a), "r"(b), "r"(c), "r"(d) : "memory");
}
__device__ __forceinline__ void red_bf16x4(uint32_t* p, uint32_t a, uint32_t b) {
  asm volatile("red.relaxed.gpu.global.add.noftz.v2.bf16x2 [%0], {%1,%2};" ::"l"(p), "r"(a), "r"(b) : "memory");
}
constexpr int SPIN_MAX = 1 << 20;
__device__ __forceinline__ uint32_t ld_acq(const void* p) { uint32_t v; asm volatile("ld.acquire.gpu.global.b32 %0, [%1];" : "=r"(v) : "l"(p) : "memory"); return v; }
template <bool ACQ = false> __device__ __forceinline__ void wait_cnt(const unsigned* p, unsigned target) {
  int it = 0;
  while (any((int)((ACQ ? ld_acq(p) : ld_rlx(p)) - target) < 0) && ++it < SPIN_MAX) {}
}
__device__ __forceinline__ uint32_t pack_bf16(float lo, float hi) { uint32_t r; asm("cvt.rn.bf16x2.f32 %0, %1, %2;" : "=r"(r) : "f"(hi), "f"(lo)); return r; }
__device__ __forceinline__ float bf_lo(uint32_t v) { return __uint_as_float(v << 16); }
__device__ __forceinline__ float bf_hi(uint32_t v) { return __uint_as_float(v & 0xffff0000u); }
__device__ __forceinline__ uint32_t hadd2(uint32_t a, uint32_t b) { uint32_t r; asm("add.rn.bf16x2 %0, %1, %2;" : "=r"(r) : "r"(a), "r"(b)); return r; }
__device__ __forceinline__ uint32_t hmul2(uint32_t a, uint32_t b) { uint32_t r; asm("mul.rn.bf16x2 %0, %1, %2;" : "=r"(r) : "r"(a), "r"(b)); return r; }
__device__ __forceinline__ uint32_t hfma2(uint32_t a, uint32_t b, uint32_t c) { uint32_t r; asm("fma.rn.bf16x2 %0, %1, %2, %3;" : "=r"(r) : "r"(a), "r"(b), "r"(c)); return r; }
__device__ __forceinline__ float rbf(float x) { uint32_t r; asm("cvt.rn.bf16x2.f32 %0, %1, %2;" : "=r"(r) : "f"(x), "f"(0.0f)); return __uint_as_float(r); }
__device__ __forceinline__ void stmatrix4(uint32_t a, uint32_t r0, uint32_t r1, uint32_t r2, uint32_t r3) {
  asm volatile("stmatrix.sync.aligned.m8n8.x4.shared.b16 [%0], {%1,%2,%3,%4};" ::"r"(a), "r"(r0), "r"(r1), "r"(r2), "r"(r3) : "memory");
}
__device__ __forceinline__ void stmatrix2(uint32_t a, uint32_t r0, uint32_t r1) {
  asm volatile("stmatrix.sync.aligned.m8n8.x2.shared.b16 [%0], {%1,%2};" ::"r"(a), "r"(r0), "r"(r1) : "memory");
}
__device__ __forceinline__ void stmatrix4t(uint32_t a, uint32_t r0, uint32_t r1, uint32_t r2, uint32_t r3) {
  asm volatile("stmatrix.sync.aligned.m8n8.x4.trans.shared.b16 [%0], {%1,%2,%3,%4};" ::"r"(a), "r"(r0), "r"(r1), "r"(r2), "r"(r3) : "memory");
}
__device__ __forceinline__ uint32_t movm(uint32_t a) { uint32_t r; asm("movmatrix.sync.aligned.m8n8.trans.b16 %0, %1;" : "=r"(r) : "r"(a)); return r; }
template <bool ACC> __device__ __forceinline__ void mma16(float* d, uint32_t a0, uint32_t a1, uint32_t a2, uint32_t a3, uint32_t b0, uint32_t b1) {
  if (ACC) asm("mma.sync.aligned.m16n8k16.row.col.f32.bf16.bf16.f32 {%0,%1,%2,%3}, {%4,%5,%6,%7}, {%8,%9}, {%0,%1,%2,%3};"
               : "+f"(d[0]), "+f"(d[1]), "+f"(d[2]), "+f"(d[3]) : "r"(a0), "r"(a1), "r"(a2), "r"(a3), "r"(b0), "r"(b1));
  else asm("mma.sync.aligned.m16n8k16.row.col.f32.bf16.bf16.f32 {%0,%1,%2,%3}, {%4,%5,%6,%7}, {%8,%9}, {%10,%10,%10,%10};"
           : "=f"(d[0]), "=f"(d[1]), "=f"(d[2]), "=f"(d[3]) : "r"(a0), "r"(a1), "r"(a2), "r"(a3), "r"(b0), "r"(b1), "f"(0.f));
}
__device__ __forceinline__ uint32_t pin(uint32_t v) { uint32_t r; asm volatile("shfl.sync.bfly.b32 %0, %1, 0, 31, 0xffffffff;" : "=r"(r) : "r"(v)); return r; }
template <class T> __device__ __forceinline__ T* pin(T* p) {
  const uint64_t a = reinterpret_cast<uint64_t>(p);
  return reinterpret_cast<T*>((uint64_t)pin((uint32_t)a) | ((uint64_t)pin((uint32_t)(a >> 32)) << 32));
}
__device__ __forceinline__ uint32_t upin(uint32_t v) { return __shfl_sync(0xffffffffu, v, 0); }
template <class T> __device__ __forceinline__ T* upin(T* p) {
  const uint64_t a = reinterpret_cast<uint64_t>(p);
  return reinterpret_cast<T*>((uint64_t)upin((uint32_t)a) | ((uint64_t)upin((uint32_t)(a >> 32)) << 32));
}
__device__ __forceinline__ bool elect() {
  uint32_t p;
  asm volatile("{\n.reg .pred P;\nelect.sync _|P, 0xffffffff;\nselp.u32 %0, 1, 0, P;\n}" : "=r"(p));
  return p;
}
__device__ __forceinline__ uint32_t set_tag(uint32_t w, uint32_t tag) { uint32_t r; asm("lop3.b32 %0, %1, 0xfffffffe, %2, 0xea;" : "=r"(r) : "r"(w), "r"(tag)); return r; }
__device__ __forceinline__ uint32_t bitsel(uint32_t w, uint32_t m, uint32_t o) { uint32_t r; asm("lop3.b32 %0, %1, %2, %3, 0xe2;" : "=r"(r) : "r"(w), "r"(m), "r"(o)); return r; }
__device__ __forceinline__ uint32_t or3(uint32_t a, uint32_t b, uint32_t c) { uint32_t r; asm("lop3.b32 %0, %1, %2, %3, 0xfe;" : "=r"(r) : "r"(a), "r"(b), "r"(c)); return r; }
__device__ __forceinline__ uint32_t diff2(uint32_t a, uint32_t b, uint32_t tag) { uint32_t r; asm("lop3.b32 %0, %1, %2, %3, 0x7e;" : "=r"(r) : "r"(a), "r"(b), "r"(tag)); return r; }
__device__ __forceinline__ float2 cmul(float2 a, float2 b) { return make_float2(a.x * b.x - a.y * b.y, a.x * b.y + a.y * b.x); }

template<int TB> __device__ __forceinline__ void wgmma_ss_160_0(float (&d)[96], uint32_t al, uint32_t ah, uint32_t bl, uint32_t bh) {
  asm volatile("{\n.reg .b64 da, db;\nmov.b64 da, {%80, %81};\nmov.b64 db, {%82, %83};\n"
    "wgmma.mma_async.sync.aligned.m64n160k16.f32.bf16.bf16 {%0,%1,%2,%3,%4,%5,%6,%7,%8,%9,%10,%11,%12,%13,%14,%15,%16,%17,%18,%19,%20,%21,%22,%23,%24,%25,%26,%27,%28,%29,%30,%31,%32,%33,%34,%35,%36,%37,%38,%39,%40,%41,%42,%43,%44,%45,%46,%47,%48,%49,%50,%51,%52,%53,%54,%55,%56,%57,%58,%59,%60,%61,%62,%63,%64,%65,%66,%67,%68,%69,%70,%71,%72,%73,%74,%75,%76,%77,%78,%79}, da, db, 1, 1, 1, 1, %84;\n}\n"
    : "+f"(d[0]),"+f"(d[1]),"+f"(d[2]),"+f"(d[3]),"+f"(d[4]),"+f"(d[5]),"+f"(d[6]),"+f"(d[7]),"+f"(d[8]),"+f"(d[9]),"+f"(d[10]),"+f"(d[11]),"+f"(d[12]),"+f"(d[13]),"+f"(d[14]),"+f"(d[15]),"+f"(d[16]),"+f"(d[17]),"+f"(d[18]),"+f"(d[19]),"+f"(d[20]),"+f"(d[21]),"+f"(d[22]),"+f"(d[23]),"+f"(d[24]),"+f"(d[25]),"+f"(d[26]),"+f"(d[27]),"+f"(d[28]),"+f"(d[29]),"+f"(d[30]),"+f"(d[31]),"+f"(d[32]),"+f"(d[33]),"+f"(d[34]),"+f"(d[35]),"+f"(d[36]),"+f"(d[37]),"+f"(d[38]),"+f"(d[39]),"+f"(d[40]),"+f"(d[41]),"+f"(d[42]),"+f"(d[43]),"+f"(d[44]),"+f"(d[45]),"+f"(d[46]),"+f"(d[47]),"+f"(d[48]),"+f"(d[49]),"+f"(d[50]),"+f"(d[51]),"+f"(d[52]),"+f"(d[53]),"+f"(d[54]),"+f"(d[55]),"+f"(d[56]),"+f"(d[57]),"+f"(d[58]),"+f"(d[59]),"+f"(d[60]),"+f"(d[61]),"+f"(d[62]),"+f"(d[63]),"+f"(d[64]),"+f"(d[65]),"+f"(d[66]),"+f"(d[67]),"+f"(d[68]),"+f"(d[69]),"+f"(d[70]),"+f"(d[71]),"+f"(d[72]),"+f"(d[73]),"+f"(d[74]),"+f"(d[75]),"+f"(d[76]),"+f"(d[77]),"+f"(d[78]),"+f"(d[79])
    : "r"(al), "r"(ah), "r"(bl), "r"(bh), "n"(TB));
}
template<int TB> __device__ __forceinline__ void wgmma_ss_144_0(float (&d)[96], uint32_t al, uint32_t ah, uint32_t bl, uint32_t bh) {
  asm volatile("{\n.reg .b64 da, db;\nmov.b64 da, {%72, %73};\nmov.b64 db, {%74, %75};\n"
    "wgmma.mma_async.sync.aligned.m64n144k16.f32.bf16.bf16 {%0,%1,%2,%3,%4,%5,%6,%7,%8,%9,%10,%11,%12,%13,%14,%15,%16,%17,%18,%19,%20,%21,%22,%23,%24,%25,%26,%27,%28,%29,%30,%31,%32,%33,%34,%35,%36,%37,%38,%39,%40,%41,%42,%43,%44,%45,%46,%47,%48,%49,%50,%51,%52,%53,%54,%55,%56,%57,%58,%59,%60,%61,%62,%63,%64,%65,%66,%67,%68,%69,%70,%71}, da, db, 1, 1, 1, 1, %76;\n}\n"
    : "+f"(d[0]),"+f"(d[1]),"+f"(d[2]),"+f"(d[3]),"+f"(d[4]),"+f"(d[5]),"+f"(d[6]),"+f"(d[7]),"+f"(d[8]),"+f"(d[9]),"+f"(d[10]),"+f"(d[11]),"+f"(d[12]),"+f"(d[13]),"+f"(d[14]),"+f"(d[15]),"+f"(d[16]),"+f"(d[17]),"+f"(d[18]),"+f"(d[19]),"+f"(d[20]),"+f"(d[21]),"+f"(d[22]),"+f"(d[23]),"+f"(d[24]),"+f"(d[25]),"+f"(d[26]),"+f"(d[27]),"+f"(d[28]),"+f"(d[29]),"+f"(d[30]),"+f"(d[31]),"+f"(d[32]),"+f"(d[33]),"+f"(d[34]),"+f"(d[35]),"+f"(d[36]),"+f"(d[37]),"+f"(d[38]),"+f"(d[39]),"+f"(d[40]),"+f"(d[41]),"+f"(d[42]),"+f"(d[43]),"+f"(d[44]),"+f"(d[45]),"+f"(d[46]),"+f"(d[47]),"+f"(d[48]),"+f"(d[49]),"+f"(d[50]),"+f"(d[51]),"+f"(d[52]),"+f"(d[53]),"+f"(d[54]),"+f"(d[55]),"+f"(d[56]),"+f"(d[57]),"+f"(d[58]),"+f"(d[59]),"+f"(d[60]),"+f"(d[61]),"+f"(d[62]),"+f"(d[63]),"+f"(d[64]),"+f"(d[65]),"+f"(d[66]),"+f"(d[67]),"+f"(d[68]),"+f"(d[69]),"+f"(d[70]),"+f"(d[71])
    : "r"(al), "r"(ah), "r"(bl), "r"(bh), "n"(TB));
}
template<int TB> __device__ __forceinline__ void wgmma_ss_96_0(float (&d)[96], uint32_t al, uint32_t ah, uint32_t bl, uint32_t bh) {
  asm volatile("{\n.reg .b64 da, db;\nmov.b64 da, {%48, %49};\nmov.b64 db, {%50, %51};\n"
    "wgmma.mma_async.sync.aligned.m64n96k16.f32.bf16.bf16 {%0,%1,%2,%3,%4,%5,%6,%7,%8,%9,%10,%11,%12,%13,%14,%15,%16,%17,%18,%19,%20,%21,%22,%23,%24,%25,%26,%27,%28,%29,%30,%31,%32,%33,%34,%35,%36,%37,%38,%39,%40,%41,%42,%43,%44,%45,%46,%47}, da, db, 1, 1, 1, 1, %52;\n}\n"
    : "+f"(d[0]),"+f"(d[1]),"+f"(d[2]),"+f"(d[3]),"+f"(d[4]),"+f"(d[5]),"+f"(d[6]),"+f"(d[7]),"+f"(d[8]),"+f"(d[9]),"+f"(d[10]),"+f"(d[11]),"+f"(d[12]),"+f"(d[13]),"+f"(d[14]),"+f"(d[15]),"+f"(d[16]),"+f"(d[17]),"+f"(d[18]),"+f"(d[19]),"+f"(d[20]),"+f"(d[21]),"+f"(d[22]),"+f"(d[23]),"+f"(d[24]),"+f"(d[25]),"+f"(d[26]),"+f"(d[27]),"+f"(d[28]),"+f"(d[29]),"+f"(d[30]),"+f"(d[31]),"+f"(d[32]),"+f"(d[33]),"+f"(d[34]),"+f"(d[35]),"+f"(d[36]),"+f"(d[37]),"+f"(d[38]),"+f"(d[39]),"+f"(d[40]),"+f"(d[41]),"+f"(d[42]),"+f"(d[43]),"+f"(d[44]),"+f"(d[45]),"+f"(d[46]),"+f"(d[47])
    : "r"(al), "r"(ah), "r"(bl), "r"(bh), "n"(TB));
}
template<int TB> __device__ __forceinline__ void wgmma_ss_96_48(float (&d)[96], uint32_t al, uint32_t ah, uint32_t bl, uint32_t bh) {
  asm volatile("{\n.reg .b64 da, db;\nmov.b64 da, {%48, %49};\nmov.b64 db, {%50, %51};\n"
    "wgmma.mma_async.sync.aligned.m64n96k16.f32.bf16.bf16 {%0,%1,%2,%3,%4,%5,%6,%7,%8,%9,%10,%11,%12,%13,%14,%15,%16,%17,%18,%19,%20,%21,%22,%23,%24,%25,%26,%27,%28,%29,%30,%31,%32,%33,%34,%35,%36,%37,%38,%39,%40,%41,%42,%43,%44,%45,%46,%47}, da, db, 1, 1, 1, 1, %52;\n}\n"
    : "+f"(d[48]),"+f"(d[49]),"+f"(d[50]),"+f"(d[51]),"+f"(d[52]),"+f"(d[53]),"+f"(d[54]),"+f"(d[55]),"+f"(d[56]),"+f"(d[57]),"+f"(d[58]),"+f"(d[59]),"+f"(d[60]),"+f"(d[61]),"+f"(d[62]),"+f"(d[63]),"+f"(d[64]),"+f"(d[65]),"+f"(d[66]),"+f"(d[67]),"+f"(d[68]),"+f"(d[69]),"+f"(d[70]),"+f"(d[71]),"+f"(d[72]),"+f"(d[73]),"+f"(d[74]),"+f"(d[75]),"+f"(d[76]),"+f"(d[77]),"+f"(d[78]),"+f"(d[79]),"+f"(d[80]),"+f"(d[81]),"+f"(d[82]),"+f"(d[83]),"+f"(d[84]),"+f"(d[85]),"+f"(d[86]),"+f"(d[87]),"+f"(d[88]),"+f"(d[89]),"+f"(d[90]),"+f"(d[91]),"+f"(d[92]),"+f"(d[93]),"+f"(d[94]),"+f"(d[95])
    : "r"(al), "r"(ah), "r"(bl), "r"(bh), "n"(TB));
}
__device__ __forceinline__ void wgmma_rs_72(float (&d)[36], uint32_t a0, uint32_t a1, uint32_t a2, uint32_t a3, uint32_t bl, uint32_t bh, int sd) {
  asm volatile("{\n.reg .pred p;\n.reg .b64 db;\nsetp.ne.b32 p, %42, 0;\nmov.b64 db, {%40, %41};\n"
    "wgmma.mma_async.sync.aligned.m64n72k16.f32.bf16.bf16 {%0,%1,%2,%3,%4,%5,%6,%7,%8,%9,%10,%11,%12,%13,%14,%15,%16,%17,%18,%19,%20,%21,%22,%23,%24,%25,%26,%27,%28,%29,%30,%31,%32,%33,%34,%35}, {%36,%37,%38,%39}, db, p, 1, 1, 1;\n}\n"
    : "+f"(d[0]),"+f"(d[1]),"+f"(d[2]),"+f"(d[3]),"+f"(d[4]),"+f"(d[5]),"+f"(d[6]),"+f"(d[7]),"+f"(d[8]),"+f"(d[9]),"+f"(d[10]),"+f"(d[11]),"+f"(d[12]),"+f"(d[13]),"+f"(d[14]),"+f"(d[15]),"+f"(d[16]),"+f"(d[17]),"+f"(d[18]),"+f"(d[19]),"+f"(d[20]),"+f"(d[21]),"+f"(d[22]),"+f"(d[23]),"+f"(d[24]),"+f"(d[25]),"+f"(d[26]),"+f"(d[27]),"+f"(d[28]),"+f"(d[29]),"+f"(d[30]),"+f"(d[31]),"+f"(d[32]),"+f"(d[33]),"+f"(d[34]),"+f"(d[35])
    : "r"(a0), "r"(a1), "r"(a2), "r"(a3), "r"(bl), "r"(bh), "r"(sd));
}
__device__ __forceinline__ void wgmma_rs_48(float (&d)[24], uint32_t a0, uint32_t a1, uint32_t a2, uint32_t a3, uint32_t bl, uint32_t bh, int sd) {
  asm volatile("{\n.reg .pred p;\n.reg .b64 db;\nsetp.ne.b32 p, %30, 0;\nmov.b64 db, {%28, %29};\n"
    "wgmma.mma_async.sync.aligned.m64n48k16.f32.bf16.bf16 {%0,%1,%2,%3,%4,%5,%6,%7,%8,%9,%10,%11,%12,%13,%14,%15,%16,%17,%18,%19,%20,%21,%22,%23}, {%24,%25,%26,%27}, db, p, 1, 1, 1;\n}\n"
    : "+f"(d[0]),"+f"(d[1]),"+f"(d[2]),"+f"(d[3]),"+f"(d[4]),"+f"(d[5]),"+f"(d[6]),"+f"(d[7]),"+f"(d[8]),"+f"(d[9]),"+f"(d[10]),"+f"(d[11]),"+f"(d[12]),"+f"(d[13]),"+f"(d[14]),"+f"(d[15]),"+f"(d[16]),"+f"(d[17]),"+f"(d[18]),"+f"(d[19]),"+f"(d[20]),"+f"(d[21]),"+f"(d[22]),"+f"(d[23])
    : "r"(a0), "r"(a1), "r"(a2), "r"(a3), "r"(bl), "r"(bh), "r"(sd));
}
template<int N,int OFF,int TB> __device__ __forceinline__ void wgmma_ss(float (&d)[96], uint32_t al, uint32_t ah, uint32_t bl, uint32_t bh) {
  if constexpr (N==160 && OFF==0) wgmma_ss_160_0<TB>(d, al, ah, bl, bh);
  else if constexpr (N==144 && OFF==0) wgmma_ss_144_0<TB>(d, al, ah, bl, bh);
  else if constexpr (N==96 && OFF==0) wgmma_ss_96_0<TB>(d, al, ah, bl, bh);
  else if constexpr (N==96 && OFF==48) wgmma_ss_96_48<TB>(d, al, ah, bl, bh);
}

__device__ __forceinline__ void dft3(float2& a, float2& b, float2& c) {
  const float s = 0.86602540378443864676f;
  float2 t = make_float2(b.x + c.x, b.y + c.y), d = make_float2(b.x - c.x, b.y - c.y);
  float2 m = make_float2(fmaf(-0.5f, t.x, a.x), fmaf(-0.5f, t.y, a.y));
  a = make_float2(a.x + t.x, a.y + t.y);
  b = make_float2(fmaf(s, d.y, m.x), fmaf(-s, d.x, m.y));
  c = make_float2(fmaf(-s, d.y, m.x), fmaf(s, d.x, m.y));
}
__device__ __forceinline__ void dft9(float2 (&x)[9]) {
  const float2 w1 = make_float2(0.76604444311897803520f, -0.64278760968653932632f);
  const float2 w2 = make_float2(0.17364817766693034885f, -0.98480775301220805937f);
  const float2 w4 = make_float2(-0.93969262078590838405f, -0.34202014332566873304f);
  dft3(x[0], x[3], x[6]); dft3(x[1], x[4], x[7]); dft3(x[2], x[5], x[8]);
  x[4] = cmul(x[4], w1); x[7] = cmul(x[7], w2); x[5] = cmul(x[5], w2); x[8] = cmul(x[8], w4);
  dft3(x[0], x[1], x[2]); dft3(x[3], x[4], x[5]); dft3(x[6], x[7], x[8]);
  float2 t;
  t = x[1]; x[1] = x[3]; x[3] = t;
  t = x[2]; x[2] = x[6]; x[6] = t;
  t = x[5]; x[5] = x[7]; x[7] = t;
}

__device__ __forceinline__ uint32_t* mod_ptr(Scratch* sc, int u, int t128) {
  const int i = t128 & 15;
  return u < 72 ? sc->moda + (t128 >> 4) * (2 * D_) + 16 * u + 2 * (i & 7) + (i >> 3) : sc->mod + 16 * (u - 72) + i;
}
__device__ __forceinline__ void mod_unit(Scratch* sc, int u, int t128, uint32_t sw_, uint32_t bar, int ph, uint32_t rb, uint32_t tag) {
  const int w = t128 >> 5, l = t128 & 31;
  uint32_t b[18];
#pragma unroll
  for (int i = 0; i < 18; i++) b[i] = lds(red + 512 + (72 * w + 4 * i + (l & 3)) * 4);
  const uint32_t sa = pin(sw_ + (144 * w + (l & 7) + 8 * (l >> 4)) * 32 + (((l >> 3) ^ (l >> 2)) & 1) * 16);
  const uint32_t sr = pin(rb + (l >> 2) * 16 + w * 4);
  uint32_t* const dst = pin(mod_ptr(sc, u, t128));
  const int kind = u / 36;
  const float mul = __uint_as_float(pin(__float_as_uint(kind == 0 ? 16.0f : 1.0f))), add = __uint_as_float(pin(__float_as_uint(kind == 1 || kind == 4 ? 1.0f : 0.0f)));
  mbar_wait(bar, ph);
  if (t128 == 0 && u < 72) TS(10);
  float d[3][4];
#pragma unroll
  for (int i = 0; i < 9; i++) {
    uint32_t a0, a1, a2, a3;
    asm volatile("ldmatrix.sync.aligned.m8n8.x4.trans.shared.b16 {%0,%1,%2,%3}, [%4];" : "=r"(a0), "=r"(a1), "=r"(a2), "=r"(a3) : "r"(sa + i * 512) : "memory");
    if (i < 3) mma16<false>(d[i], a0, a1, a2, a3, b[2 * i], b[2 * i + 1]);
    else mma16<true>(d[i % 3], a0, a1, a2, a3, b[2 * i], b[2 * i + 1]);
  }
  if ((l & 3) == 0) { sts(sr, __float_as_uint(d[0][0] + d[1][0] + d[2][0])); sts(sr + 128, __float_as_uint(d[0][2] + d[1][2] + d[2][2])); }
  bar_sync(4, 128);
  const uint4 v = lds4(rb + (l & 15) * 16);
  const float m = rbf(fmaf(rbf((__uint_as_float(v.x) + __uint_as_float(v.y)) + (__uint_as_float(v.z) + __uint_as_float(v.w))), mul, add));
  if (u < 72 || t128 < 16) *dst = __float_as_uint(m) | tag;
}

__device__ __forceinline__ float rsq(float x) { float r; asm("rsqrt.approx.ftz.f32 %0, %1;" : "=f"(r) : "f"(x)); return r; }
__device__ __forceinline__ void ln_stats2(const float (&a)[18], const float (&b)[18], float sc, float& oa, float& ra, float& ob, float& rb) {
  float v[4] = {0.f, 0.f, 0.f, 0.f}, w[4] = {0.f, 0.f, 0.f, 0.f};
#pragma unroll
  for (int i = 0; i < 18; i += 2) {
    v[0] += a[i]; v[1] = fmaf(a[i], a[i], v[1]); v[2] += b[i]; v[3] = fmaf(b[i], b[i], v[3]);
    w[0] += a[i + 1]; w[1] = fmaf(a[i + 1], a[i + 1], w[1]); w[2] += b[i + 1]; w[3] = fmaf(b[i + 1], b[i + 1], w[3]);
  }
#pragma unroll
  for (int e = 0; e < 4; e++) v[e] += w[e];
#pragma unroll
  for (int o = 16; o; o >>= 1) {
#pragma unroll
    for (int e = 0; e < 4; e++) v[e] += __shfl_xor_sync(0xffffffffu, v[e], o);
  }
  const float ma = v[0] * (1.0f / D_), mb = v[2] * (1.0f / D_);
  ra = sc * rsq(fmaxf(fmaf(-ma, ma, v[1] * (1.0f / D_)), 0.f) + 1e-5f);
  rb = sc * rsq(fmaxf(fmaf(-mb, mb, v[3] * (1.0f / D_)), 0.f) + 1e-5f);
  oa = -ma * ra; ob = -mb * rb;
}

__device__ __forceinline__ float tmat(int c, int q, int j) {
  const int ph = q == 1 ? 1024 * j : (q >> 1) * (c + 128 * j) + 512 * (q & 1);
  return __cosf((float)(((ph + 1024) & 2047) - 1024) * (6.283185307179586f / 2048.0f));
}
__device__ __forceinline__ uint32_t line_off(int k1, int kap, int pi, int f) {
  int kd = 64 * k1 + 9 * kap;
  if (kap == 0 && k1 > 4) kd -= 288;
  if (kd >= D_) kd -= D_;
  return pi * 2400 + ((min(kd, D_ - kd) ^ f) << 3);
}

constexpr int JSK = 5;
struct Ring { uint32_t st, ph; };
template <bool G2, class T> __device__ __forceinline__ void ring_next(T& st, T& ph) {
  if (++st == NST) st = 0;
  ph ^= ((G2 ? 0xDu : 0x1u) >> st) & 1;
}
__device__ __forceinline__ void arrive_if(uint32_t a, uint32_t p) {
  asm volatile("{\n.reg .pred p;\nsetp.ne.u32 p, %1, 0;\n@p mbarrier.arrive.shared::cta.b64 _, [%0];\n}" ::"r"(a), "r"(p) : "memory");
}
template <int NA> __device__ __forceinline__ void reg_fence_n(float (&d)[96]) {
#pragma unroll
  for (int i = 0; i < NA; i++) asm volatile("" : "+f"(d[i])::"memory");
}
template <int MODE>
__device__ __forceinline__ void gemm_main(float (&acc)[96], uint32_t da0, uint32_t da1, uint32_t db0, int wg, Ring& rg,
                                          bool rows, uint32_t* x1p, const uint32_t (&xr)[18]) {
  static_assert(JSK == NST - 1, "the held slot is the first one that is not refilled by GEMM1");
  constexpr int NKB = MODE == 3 ? 36 : 32, J = MODE == 3 ? J2 : JSK;
  constexpr uint32_t HA = 0x40000040u, HB = MODE == 3 ? 0x40000040u : 0x80000020u;
  constexpr uint32_t KA = 2048 >> 4, KB = MODE == 3 ? (32 >> 4) : (1024 >> 4);
  constexpr int NA = MODE == 3 ? 72 : MODE == 1 ? 96 : 80;
  const uint32_t t = threadIdx.x & 127;
  const uint32_t eb = full0 + 8 * NST;
  uint32_t pb = 0, rel = t == 0, prel = 0, ok = 0;
  int n = MODE == 3 ? NKB - J : X1K + 2 * wg;
#pragma unroll 1
  for (int pass = MODE == 3 ? 0 : -1;; pass++) {
#pragma unroll 1
    do {
      const uint32_t so = rg.st * ((MODE == 3 ? STAGE2 : STAGE) >> 4), cb = eb + 8 * rg.st;
      if (__builtin_expect(!ok, 0)) mbar_wait(full0 + 8 * rg.st, rg.ph);
      reg_fence_n<NA>(acc);
      if (MODE == 1 && wg) {
        wg_fence();
#pragma unroll
        for (int k = 0; k < 4; k++) wgmma_ss<96, 48, 1>(acc, da1 + so + k * KA, HA, db0 + so + k * KB, HB);
        wg_commit();
      }
      wg_fence();
#pragma unroll
      for (int k = 0; k < 4; k++) {
        if (k == 3) { ring_next<MODE == 3>(rg.st, rg.ph); ok = PEEK ? mbar_test(full0 + 8 * rg.st, rg.ph) : 0; }
        if (MODE == 0) wgmma_ss<160, 0, 1>(acc, da0 + so + k * KA, HA, db0 + so + k * KB, HB);
        else if (MODE == 3) wgmma_ss<144, 0, 0>(acc, da0 + so + k * KA, HA, db0 + so + k * KB, HB);
        else wgmma_ss<96, 0, 1>(acc, da0 + so + k * KA, HA, db0 + so + k * KB, HB);
      }
      wg_commit();
      wg_wait<1>();
      reg_fence_n<NA>(acc);
      arrive_if(pb, prel);
      pb = cb; prel = rel;
    } while (--n);
    if (pass == 2 - wg) break;
    if (MODE != 3 && pass < 0) {
      if (rows) {
#pragma unroll
        for (int i = 0; i < 9; i++) { x1p[32 * i] = xr[i]; x1p[128 * 288 + 32 * i] = xr[9 + i]; }
      }
      n = NKB - JSK - X1K - 2 * wg;
      continue;
    }
    n = 1;
    if (pass == 0) {
      if (MODE != 3) prel = rel & wg;
      else { rel = 0; if (J < NST) prel = 0; }
      n = J - 1 + wg;
      if (!wg) continue;
      wg_wait<0>();
      arrive_if(pb, prel);
      prel = 0;
    }
    bar_sync(1, 256);
  }
  wg_wait<0>();
  reg_fence_n<NA>(acc);
  if (MODE != 3) arrive_if(pb, MODE == 1 ? prel & ~wg : prel);
}

constexpr float GK1 = 2.0f * 0.7978845608028654f, GK3 = 8.0f * 0.044715f * 0.7978845608028654f;

__device__ __forceinline__ int kb2_order(int i) { const int wv = i / 6; return 6 * (i - 6 * wv) + ((0x431250 >> (4 * wv)) & 7); }

__device__ __forceinline__ int kb2_pos(int kb) { const int hf = kb >= 36, k = kb - 36 * hf, gr = k / 6; return 64 * hf + gr + 6 * ((0x154230 >> (4 * (k - 6 * gr))) & 7); }

__device__ __forceinline__ void wait_flags(const unsigned* p, int idx, unsigned target, uint32_t& ready) {
  int it = 0;
  while (!((ready >> idx) & 1) && it++ < SPIN_MAX) ready = __ballot_sync(0xffffffffu, (int)(ld_rlx(p) - target) >= 0);
}

enum { B_FULL = 0, B_EMPTY = 6, B_S4 = 12, B_S5, B_LAND, B_FLT = B_LAND + 6, B_Z1, B_Z2, B_GO, B_X, B_WM, B_NUM, B_W0 = B_NUM };

__global__ void __launch_bounds__(NTHR, 1)
fused_kernel(const Params p, const __grid_constant__ Maps maps) {
  extern __shared__ __align__(1024) uint8_t smem_raw[];
  const int bx = blockIdx.x, cta = bx < 112 || bx >= 130 ? bx : bx < 114 ? bx + 16 : bx - 2;
  const int tid = threadIdx.x, t128 = tid & 127;
  const int wp = __shfl_sync(0xffffffffu, tid >> 5, 0), wg = wp >> 2;
  const int l = tid & 31, g = l >> 2, t = l & 3;
  Scratch* const sc = p.s;
  const bool rows = cta < 128;
  const int mu = rows ? cta + 4 : cta - 128;
  const int R = mu - 12;

  uint32_t xr[18];
  uint32_t cv[3];
  const unsigned ep0 = ld_rlx(&sc->cnt[C_EP]);
  if (tid == 0) TS(0);
  if (wg == 2) {
#pragma unroll
    for (int i = 0; i < 3; i++) cv[i] = ld_nc(reinterpret_cast<const uint32_t*>(p.c) + min(t128 + 128 * i, 287));
    if (wp == 9 && l < 9 && rows) {
      const int h = 9 * cta + l;
      prefetch_l2(reinterpret_cast<const uint8_t*>(p.wmod) + (size_t)(h >> 1) * (12 * D_) + (h & 1) * (2 * D_), 2 * D_);
    }
    if (tid == 256 && mu < 72) {
      mbar_init(full0 + 8 * B_W0, 1);
      fence_async_smem();
      mbar_expect(full0 + 8 * B_W0, 18432);
#pragma unroll 1
      for (int i = 0; i < 3; i++) tma2d(sbase + O_P2 + i * 6144, &maps.wm, 16 * mu, 192 * i, full0 + 8 * B_W0);
    }
    __syncwarp();
#pragma unroll 1
    for (int u = mu < 72 ? mu : 72 + mu; u < 216; u += u < 72 ? 72 : NCTA) if (u < 72 || t128 < 16) *mod_ptr(sc, u, t128) = 0;
    if (wp == 11 && smem_u32(smem_raw) != sbase) __trap();
    if (wp >= 10 && elect()) {
#pragma unroll 1
      for (int i = wp - 10; i < B_NUM; i += 2) mbar_init(full0 + 8 * i, i == B_FLT ? 4 : i == B_WM ? 3 : i < B_LAND && i != B_S4 ? 2 : 1);
      fence_async_smem();
    }
    __syncwarp();
  } else if (rows) {
    const uint32_t* xs = reinterpret_cast<const uint32_t*>(p.x) + (size_t)(cta + 256 * wp) * 288 + l;
#pragma unroll
    for (int i = 0; i < 9; i++) { xr[i] = ld_nc(xs + 32 * i); xr[9 + i] = ld_nc(xs + 128 * 288 + 32 * i); }
  }
  CK(0);
  if (tid == 64 && cta == NCTA - 1) prefetch_l2(p.tab, sizeof(T_TAB));
  __syncwarp();
  auto tag_of = [](unsigned e) { return (e & 0x7fffu) | 0x8000u; };
  const int kap = 8 * ((wp & 3) ^ (wg & 1)) + g;
  uint32_t tb[4], sb1[3], lo[9];
#pragma unroll
  for (int i = 0; i < 4; i++) tb[i] = pin(pack_bf16(tmat(cta, 8 * (i >> 1) + g, 2 * t + 8 * (i & 1)), tmat(cta, 8 * (i >> 1) + g, 2 * t + 8 * (i & 1) + 1)));
#pragma unroll
  for (int i = 0; i < 3; i++) {
    const int d = 48 * wp + 16 * i + (l & 15);
    sb1[i] = pin(sbase + O_B1 + (l >> 4) * 9216 + (d % 9) * 1024 + (d & 63) * 16);
  }
#pragma unroll
  for (int k1 = 0; k1 < 9; k1++) lo[k1] = pin(sbase + O_Z1 + line_off(k1, kap, 4 * wg + t, cta & 3));
  const uint32_t snt = pin(sbase + O_NRM + ((l & 7) + 8 * (l >> 4)) * 1168 + (48 * wp + (l & 8)) * 2), sn = pin(sbase + O_NRM + wp * 2336 + l * 4);
  const uint32_t smask = pin(t ? 0u : 0xffff0000u);
  const uint32_t* const mp = pin(sc->moda + (cta >> 4) * (2 * D_) + 48 * wp + 2 * g);
  const uint4* const ftab = pin(p.tab + TB_F + (t128 ^ (wg << 5)));

  if (wg == 2) {
#pragma unroll
    for (int i = 0; i < 3; i++) {
      const float c0 = bf_lo(cv[i]), c1 = bf_hi(cv[i]);
      sts(red + 512 + min(t128 + 128 * i, 287) * 4, pack_bf16(__fdividef(c0, 1.0f + __expf(-c0)), __fdividef(c1, 1.0f + __expf(-c1))));
    }
    if (t128 == 0) sts(full0 + 248, ep0 + 1);
    if (wp == 9 && l < 11) asm volatile("prefetch.tensormap [%0];" ::"l"(&maps.z1 + l) : "memory");
    bar_sync(4, 128);
    if (mu < 72) {
      mod_unit(sc, mu, t128, sbase + O_P2, full0 + 8 * B_W0, 0, red, tag_of(upin(ep0) + 1));
      if (t128 == 0) TS(25);
    }
    CK(1);
  }
  const int pi = R / 15, col0 = 20 * (R - 15 * pi);
  const int xu = DF_ * pi + col0, xv = DF_ * (pi ? 16 - pi : 8) + col0;
  auto load_filter = [&](int a) {
    const int x = (a & 1) ? xv : xu;
    const bool wide = (x & 15) > 12;
    mbar_expect(full0 + 8 * B_FLT, wide ? 12288 : 8192);
    tma2d(sbase + O_RAW + a * 12288, &maps.wf[a & 2], x & ~15, 0, full0 + 8 * B_FLT);
    if (wide) tma2d(sbase + O_RAW + a * 12288 + 8192, &maps.wf[(a & 2) + 1], (x & ~15) + 32, 0, full0 + 8 * B_FLT);
  };
  uint4 af[4];
  if (rows) {
    uint2 ms[3], mc[3];
    auto load_mod = [&](uint32_t o = 0) {
#pragma unroll
      for (int i = 0; i < 3; i++) { ms[i] = ld_rlx2(mp + 2 * o + 16 * i); mc[i] = ld_rlx2(mp + 2 * o + D_ + 16 * i); }
    };
    if (wg < 2) {
      float a[18], b[18];
#pragma unroll
      for (int i = 0; i < 9; i++) { a[2 * i] = bf_lo(xr[i]); a[2 * i + 1] = bf_hi(xr[i]); b[2 * i] = bf_lo(xr[9 + i]); b[2 * i + 1] = bf_hi(xr[9 + i]); }
      float oa, ra, ob, rb;
      ln_stats2(a, b, 1.0f, oa, ra, ob, rb);
      CK(1);
      load_mod((__float_as_uint(ra) | __float_as_uint(rb)) >> 31);
#pragma unroll
      for (int i = 0; i < 9; i++) {
        sts(sn + i * 128, pack_bf16(fmaf(a[2 * i], ra, oa), fmaf(a[2 * i + 1], ra, oa)));
        sts(sn + 1168 + i * 128, pack_bf16(fmaf(b[2 * i], rb, ob), fmaf(b[2 * i + 1], rb, ob)));
      }
      CK(2);
      bar_arrive(10, NTHR);
#pragma unroll
      for (int kk = 0; kk < 4; kk++) af[kk] = ld_nc4(ftab + kk * 128);
      bar_sync(1, 256);
      if (tid == 0) TS(2);
    } else {
      bar_sync(10, NTHR);
      load_mod();
      CK(2);
      if (wp >= 10 && elect()) prefetch_l2(reinterpret_cast<const uint8_t*>(wp == 10 ? p.wr : p.wi) + cta * 9248, 9248);
      __syncwarp();
    }
    float rs[3][8];
#pragma unroll
    for (int i = 0; i < 3; i++) {
      uint32_t a0, a1, a2, a3;
      asm volatile("ldmatrix.sync.aligned.m8n8.x4.trans.shared.b16 {%0,%1,%2,%3}, [%4];" : "=r"(a0), "=r"(a1), "=r"(a2), "=r"(a3)
                   : "r"(snt + 32 * i) : "memory");
      mma16<false>(&rs[i][0], a0, a1, a2, a3, tb[0], tb[1]);
      mma16<false>(&rs[i][4], a0, a1, a2, a3, tb[2], tb[3]);
    }
    CK(3);
    const uint32_t tag16 = tag_of(upin(ep0) + 1), tag1 = tag16 & 1;
    {
      int it = 0;
#pragma unroll 1
      while (true) {
        uint32_t bad = 0;
#pragma unroll
        for (int i = 0; i < 3; i++) bad |= diff2(ms[i].x, ms[i].y, tag16) | diff2(mc[i].x, mc[i].y, tag16);
        if (!any(bad & 0xffffu) || ++it > SPIN_MAX) break;
        load_mod();
      }
      CK(4);
      if (tid == 0) TS(3);
#pragma unroll
      for (int i = 0; i < 3; i++) {
        const float c0 = bf_hi(mc[i].x), c1 = bf_hi(mc[i].y);
        const float s0 = __uint_as_float(ms[i].x & smask), s1 = __uint_as_float(ms[i].y & smask);
        stmatrix4(sb1[i], pack_bf16(fmaf(rs[i][0], c0, s0), rs[i][1] * c0), pack_bf16(fmaf(rs[i][2], c1, s1), rs[i][3] * c1),
                  pack_bf16(rs[i][4] * c0, rs[i][5] * c0), pack_bf16(rs[i][6] * c1, rs[i][7] * c1));
      }
    }
    fence_async_smem();
    CK(5);
    if (wg == 2) {
      bar_arrive(5, NTHR);
      if (R >= 0 && elect()) load_filter(wp - 8);
      __syncwarp();
      const int slot = 4 * (cta & 7) + ((cta >> 4) & 3) + 32 * (2 * (cta >> 6) + ((cta >> 3) & 1));
      const uint32_t c0 = upin(40 * slot), c1 = upin(60 * (wp & 1)), src = upin(sbase + O_Z1 + (wp & 1) * 9600);
      const CUtensorMap* mz = upin(&maps.z1);
      unsigned* hint = pin(sc->cnt + C_Z1 + 32 * (wp & 1));
      if (wp < 10) {
        bar_sync(2 + (wp & 1), 160);
        if (elect()) tma_st2d(mz, src, c0, c1);
        bulk_commit_wait();
        if (elect()) red_add(hint, 1);
        if (tid == 256) TS(4);
        __syncwarp();
      }
    } else {
      bar_sync(5, NTHR);
      CK(6);
      float acc[36];
      const uint32_t db = (((sbase + O_B1 + wg * 9216) & 0x3FFFF) >> 4) | ((128 >> 4) << 16);
      wg_fence();
#pragma unroll
      for (int kk = 0; kk < 4; kk++) wgmma_rs_72(acc, af[kk].x, af[kk].y, af[kk].z, af[kk].w, db + kk * 16, 1024 >> 4, kk);
      wg_commit();
      wg_wait<0>();
      reg_fence(acc);
      CK(7);
      float2 za[9], zb[9];
#pragma unroll
      for (int i = 0; i < 9; i++) { za[i] = make_float2(acc[4 * i], acc[4 * i + 2]); zb[i] = make_float2(acc[4 * i + 1], acc[4 * i + 3]); }
      dft9(za); dft9(zb);
      if ((wp & 3) == wg) {
        const float sp = g ? 0.f : 1.f;
#pragma unroll
        for (int k = 1; k < 5; k++) {
          float2 a = za[k], b = za[9 - k];
          za[k] = make_float2(fmaf(sp, b.x, a.x), fmaf(-sp, b.y, a.y)); za[9 - k] = make_float2(fmaf(-sp, a.x, b.x), fmaf(sp, a.y, b.y));
          a = zb[k]; b = zb[9 - k];
          zb[k] = make_float2(fmaf(sp, b.x, a.x), fmaf(-sp, b.y, a.y)); zb[9 - k] = make_float2(fmaf(-sp, a.x, b.x), fmaf(sp, a.y, b.y));
        }
        const uint32_t w0 = set_tag(pack_bf16(za[0].y, 0.f), tag1), w1 = pack_bf16(zb[0].y, 0.f);
        asm volatile("{\n.reg .pred p;\nsetp.eq.u32 p, %3, 0;\n@p st.shared.v2.b32 [%0], {%1,%2};\n}" ::"r"(lo[0] + 288 * 8), "r"(w0), "r"(w1), "r"(g) : "memory");
        za[0].y = g ? za[0].y : 0.f; zb[0].y = g ? zb[0].y : 0.f;
      }
#pragma unroll
      for (int k1 = 0; k1 < 9; k1++) sts2(lo[k1], set_tag(pack_bf16(za[k1].x, za[k1].y), tag1), pack_bf16(zb[k1].x, zb[k1].y));
      fence_async_smem();
      CK(8);
      bar_arrive(2 + wg, 160);
      {
        const uint32_t fx = (((cta >> 4) ^ cta) & 3) << 3, dl = O_IN - O_Z1, st = sbase + O_ST + 15360 + tid * 16;
        sts4(st, (lo[0] ^ fx) + dl, (lo[1] ^ fx) + dl, (lo[2] ^ fx) + dl, (lo[3] ^ fx) + dl);
        sts4(st + 4096, (lo[4] ^ fx) + dl, (lo[5] ^ fx) + dl, (lo[6] ^ fx) + dl, (lo[7] ^ fx) + dl);
        sts4(st + 8192, (lo[8] ^ fx) + dl, (lo[0] ^ fx) + dl + (kap ? 0 : 288 * 8),
             sbase + O_B3 + wg * 1024 + (l >> 4) * 2048 + (2 * (kap & 24) + (l & 15)) * 16, 0);
      }
    }
    {
      uint32_t sy[6];
#pragma unroll
      for (int i = 0; i < 6; i++) {
        const int rr = 16 * (wp & 3) + g + 8 * (i & 1);
        sy[i] = sbase + O_Y + (t * 584 + 64 * ((3 * wg + (i >> 1) + 63 - rr) % 9) + rr) * 4;
      }
      sts4(sbase + O_ST + tid * 16, movm(tb[0]), movm(tb[2]), movm(tb[1]), movm(tb[3]));
      sts4(sbase + O_ST + 6144 + tid * 16, sy[0], sy[1], sy[2], sy[3]);
      sts2(sbase + O_ST + 12288 + tid * 8, sy[4], sy[5]);
    }
  } else {
    __syncthreads();
  }

  const unsigned ep = upin(lds(full0 + 248));
  const uint32_t tag16 = tag_of(ep), tag1 = ep & 1;
  auto load_wm = [&](int u) {
    if (wp > 8 && elect()) {
      mbar_expect(full0 + 8 * B_WM, 6144);
      tma2d(sbase + O_NRM + (wp - 9) * 6144, &maps.wm, 16 * u, 192 * (wp - 9), full0 + 8 * B_WM);
    }
    __syncwarp();
  };
  if (R >= 0) {
    const int nl = (col0 + wp < DF_) + (wg < 2 && col0 + wp + 12 < DF_);
    uint4 cf[2][4], G[4];
#pragma unroll
    for (int i = 0; i < 4; i++) {
      cf[0][i] = __ldg(p.tab + TB_P2 + i * 32 + l);
      cf[1][i] = __ldg(p.tab + TB_P2 + (pi ? i : 4 + i) * 32 + l);
      G[i] = __ldg(p.tab + TB_P2 + (8 + i) * 32 + l);
    }
    const uint32_t* zin = sc->z1 + (size_t)R * 5120;
    if (wp == 10) {
      const uint32_t* zu = upin(zin);
      if (elect()) mbar_expect(full0 + 8 * B_Z1, 20480);
      wait_cnt(sc->cnt + C_Z1 + 32 * (pi >> 2), 128 * ep);
      if (elect()) {
        bulk_ld(sbase + O_P2, zu, 20480, full0 + 8 * B_Z1);
        TS(12);
      }
      __syncwarp();
    }
    mbar_wait(full0 + 8 * B_FLT, 0);
    CK(9);
    float wn[16], wc[16];
#pragma unroll 1
    for (int ln = nl - 1; ln >= 0; ln--) {
      const int col = col0 + wp + 12 * ln, k2 = (57 * col) & 63;
      const bool cj = k2 > 32;
      const float nr = ((col & 31) == 0 && col != 0 && col != 288 ? 0.5f : 1.0f) / ((float)S_ * D_), ni = cj ? -nr : nr;
#pragma unroll
      for (int i = 0; i < 16; i++) wn[i] = wc[i];
#pragma unroll
      for (int cl = 0; cl < 2; cl++) {
        const int v = cl ^ (cj && pi), e = ((v ? xv : xu) & 15) + wp + 12 * ln, sh = e < 32 ? 6 : 5;
        const uint32_t base = sbase + O_RAW + v * 12288 + (e < 32 ? 2 * e : 8192 - 64 + 2 * e), msk = e < 32 ? 0x30 : 0x10;
        const int dm = v ? (cj || pi ? -1 : 0) : 0;
#pragma unroll
        for (int tt = 0; tt < 4; tt++) {
          const int kc = g + 64 * (tt >> 1) + 16 * t + 8 * (tt & 1);
          uint32_t a = base + ((((cj ? -kc : kc) + dm) & 127) << sh);
          a ^= (a >> 3) & msk;
          wc[4 * tt + 2 * cl] = lds_bf(a) * nr; wc[4 * tt + 2 * cl + 1] = lds_bf(a + 24576) * ni;
        }
      }
    }
    const float al = __uint_as_float(pin((pi ? 0x3f800000u : 0u) + (l >> 5)));
    const uint32_t tagv = pin(tag1 + (l >> 5));
    CK(10);
    uint32_t off = pin(l * 160 + ((wp ^ (g & 3)) << 3));
    uint32_t offo = pin(sbase + O_P2 + 20480 + off - 64 * l), po = 3072;
    unsigned* hz2 = pin(sc->cnt + C_Z2);
    const uint32_t do2 = pin(12288 - 32 * l);
    const CUtensorMap* mz2 = upin(&maps.z2[wp == 0]);
    const uint32_t sz2 = upin(sbase + O_P2 + 20480 + (wp ? 0 : 12288)), cz2 = upin(40 * R + (wp ? 0 : 24));
    mbar_wait(full0 + 8 * B_Z1, 0);
    CK(11);
    if (tid == 0) TS(8);
    if (wg == 2) load_wm(72 + mu);
    uint2 v[4], v2[4];
    const uint32_t o2 = nl > 1 ? 96 : 0;
#pragma unroll
    for (int i = 0; i < 4; i++) { v[i] = lds2(sbase + O_P2 + off + i * 5120); v2[i] = lds2(sbase + O_P2 + off + o2 + i * 5120); }
    auto bad2 = [&]() {
      return any(or3(or3(diff2(v[0].x, v[1].x, tagv), diff2(v[2].x, v[3].x, tagv), diff2(v2[0].x, v2[1].x, tagv)), diff2(v2[2].x, v2[3].x, tagv), 0) & 1);
    };
    if (__builtin_expect(bad2() && nl, 0)) {
      FAILCNT(0);
      int it = 0;
      do {
#pragma unroll
        for (int i = 0; i < 4; i++) {
          v[i] = ld_rlx2(reinterpret_cast<const uint8_t*>(zin) + off + i * 5120);
          v2[i] = ld_rlx2(reinterpret_cast<const uint8_t*>(zin) + off + o2 + i * 5120);
        }
      } while (bad2() && ++it < SPIN_MAX);
    }
#pragma unroll 1
    for (int ln = 0; ln < nl; ln++, offo += do2, po = 2048) {
      float d[4][4];
      uint32_t A[8];
#pragma unroll
      for (int h = 0; h < 2; h++) {
        mma16<false>(d[2 * h], cf[0][0].x, cf[0][0].y, cf[0][0].z, cf[0][0].w, v[h].x, v[2 + h].x);
        mma16<false>(d[2 * h + 1], cf[1][0].x, cf[1][0].y, cf[1][0].z, cf[1][0].w, v[h].y, v[2 + h].y);
      }
      if (ln) { fence_async_smem(); bar_arrive(15, NTHR); }
#pragma unroll
      for (int h = 0; h < 2; h++)
#pragma unroll
        for (int L = 0; L < 2; L++) {
          const uint4 tw = cf[L][2 + h];
          const float* z = d[2 * h + L];
          const float2 z0 = cmul(make_float2(z[0], z[2]), make_float2(__uint_as_float(tw.x), __uint_as_float(tw.y)));
          const float2 z1 = cmul(make_float2(z[1], z[3]), make_float2(__uint_as_float(tw.z), __uint_as_float(tw.w)));
          A[4 * h + L] = pack_bf16(z0.x, z0.y); A[4 * h + 2 + L] = pack_bf16(z1.x, z1.y);
        }
#pragma unroll
      for (int tt = 0; tt < 4; tt++) {
        mma16<false>(d[tt], A[0], A[1], A[2], A[3], G[tt].x, G[tt].y);
        mma16<true>(d[tt], A[4], A[5], A[6], A[7], G[tt].z, G[tt].w);
      }
#pragma unroll
      for (int tt = 0; tt < 4; tt++) {
        const float ar = d[tt][0], aj = d[tt][1], br = d[tt][2], bj = d[tt][3];
        const float2 y1 = cmul(make_float2(fmaf(-al, bj, ar), fmaf(al, br, aj)), make_float2(wc[4 * tt], wc[4 * tt + 1]));
        const float2 y2 = cmul(make_float2(fmaf(al, ar, bj), fmaf(al, aj, -br)), make_float2(wc[4 * tt + 2], wc[4 * tt + 3]));
        A[2 * tt] = pack_bf16(fmaf(al, y2.x, y1.x), fmaf(-al, y2.y, -y1.y));
        A[2 * tt + 1] = pack_bf16(fmaf(al, y1.y, -y2.y), fmaf(al, y1.x, -y2.x));
      }
#pragma unroll
      for (int i = 0; i < 16; i++) wc[i] = wn[i];
#pragma unroll
      for (int i = 0; i < 4; i++) v[i] = v2[i];
#pragma unroll
      for (int tt = 0; tt < 4; tt++) {
        mma16<false>(d[tt], A[0], A[1], A[2], A[3], G[tt].x, G[tt].y);
        mma16<true>(d[tt], A[4], A[5], A[6], A[7], G[tt].z, G[tt].w);
      }
#pragma unroll
      for (int h = 0; h < 2; h++)
#pragma unroll
        for (int L = 0; L < 2; L++) {
          const uint4 tw = cf[L][2 + h];
          const float2 z0 = cmul(make_float2(d[2 * h][2 * L], d[2 * h][2 * L + 1]), make_float2(__uint_as_float(tw.x), __uint_as_float(tw.y)));
          const float2 z1 = cmul(make_float2(d[2 * h + 1][2 * L], d[2 * h + 1][2 * L + 1]), make_float2(__uint_as_float(tw.z), __uint_as_float(tw.w)));
          A[4 * h + 2 * L] = movm(pack_bf16(z0.x, z1.x)); A[4 * h + 2 * L + 1] = movm(pack_bf16(z0.y, z1.y));
        }
#pragma unroll
      for (int h = 0; h < 2; h++) {
        mma16<false>(d[0], cf[0][1].x, cf[0][1].y, cf[0][1].z, cf[0][1].w, A[4 * h], A[4 * h + 1]);
        mma16<false>(d[1], cf[1][1].x, cf[1][1].y, cf[1][1].z, cf[1][1].w, A[4 * h + 2], A[4 * h + 3]);
#pragma unroll
        for (int e = 0; e < 2; e++)
          sts2(offo + (2 * h + e) * po, set_tag(pack_bf16(d[0][e], d[0][2 + e]), tagv), pack_bf16(d[1][e], d[1][2 + e]));
      }
      CK(12 + ln);
    }
    fence_async_smem();
    if (nl < 2 && wp != 8) bar_arrive(15, NTHR);
    if (wp & 7) { if (wg < 2) bar_arrive(6, 256); }
    else {
      if (wp) bar_sync(15, NTHR); else bar_sync(6, 256);
      if (elect()) tma_st2d(mz2, sz2, cz2, 0);
      bulk_commit_wait();
      if (wp == 0 && elect()) red_add(hz2, 1);
      if (tid == 0) TS(9);
      __syncwarp();
    }
  }
  if (wg == 2) {
#pragma unroll 1
    for (int u = 72 + mu, k = 0; u < 216; u += NCTA, k ^= 1) {
      if (R < 0) { fence_async_smem(); bar_sync(4, 128); load_wm(u); }
      mod_unit(sc, u, t128, sbase + O_NRM, full0 + 8 * B_WM, k, red + 256 - 256 * k, tag16);
    }
    fence_async_smem();
    CK(13);
  }

  const int grp = bx / 11, m1 = bx - 11 * grp;
  const bool helper = (m1 & 3) == 3;
  const int f1 = 384 * grp + (helper ? 192 : 128) * (m1 >> 2);
  const int d1 = 160 * (m1 & 3), flip = m1 >= 7;
  const int a1bytes = helper ? 24576 : 16384;
  auto load_a1 = [&](int st, int kb) {
    mbar_expect(full0 + 8 * st, a1bytes);
    tma4d_ef(sbase + st * STAGE, helper ? &maps.w1b : &maps.w1a, 4 * (kb >> 3), 16 * (kb & 7), f1 >> 6, full0 + 8 * st);
  };

  if (rows) {
#pragma unroll
    for (int kk = 0; kk < 4; kk++) af[kk] = __ldg(p.tab + TB_E + kk * 128 + t128);
    const uint4 c0 = lds4(sbase + O_ST + tid * 16), c1 = lds4(sbase + O_ST + 6144 + tid * 16);
    const uint2 c2 = lds2(sbase + O_ST + 12288 + tid * 8);
    const uint32_t tc[4] = {c0.x, c0.y, c0.z, c0.w}, sy[6] = {c1.x, c1.y, c1.z, c1.w, c2.x, c2.y};
    const uint32_t l8 = pin(8 * l), syl = pin(sbase + O_Y + wp * 2336 + 8 * l);
    uint32_t sh3[3], ham[3];
#pragma unroll
    for (int k = 0; k < 3; k++) {
      const int pos = k && (l >> 4) == k - 1 ? (l & 8) + 4 * (l & 1) + ((l >> 1) & 3) : 4 * (l & 3) + ((l >> 2) & 3);
      const int sw = 2 * cta + (wp & 1), ph = pos ^ ((sw & 3) << 2);
      sh3[k] = pin((wp < 2 ? (l >> 4) * 4096 : sbase + O_B3 + (wp >> 1) * 4608 + (l >> 4) * 256) + (wp & 1) * 128 + ph * 4);
      const bool tg = ((ph ^ sw) & 7) == 0;
      ham[k] = pin(tg ? ~1u : ~0u);
    }
    uint8_t* const h3g = upin(sc->h3 + (cta >> 4) * (18 * 4096) + (cta & 15) * 256);
    const int slot = 4 * (cta >> 4) + ((cta >> 1) & 3) + 32 * (2 * ((cta >> 3) & 1) + (cta & 1));
    const uint32_t* zin = sc->z2 + (size_t)slot * 4800;
    uint32_t ga[9];
    uint2 sh[9], sw[9];
    auto load_mod3 = [&](int part) {
#pragma unroll
      for (int i = 0; i < 9; i++) {
        if (part != 2) { const uint2 v = lds2(l8 + sbase + O_MOD + 256 * i); ga[i] = __byte_perm(v.x, v.y, 0x7632); }
        if (part != 1) { sh[i] = lds2(l8 + sbase + O_MOD + 4 * D_ + 256 * i); sw[i] = lds2(l8 + sbase + O_MOD + 8 * D_ + 256 * i); }
      }
    };
    if (wg == 2) {
      {
        uint4 v[4];
        const int i3 = min(t128 + 384, 431);
        int it = 0;
        while (true) {
          uint32_t bad = 0;
#pragma unroll
          for (int k = 0; k < 4; k++) v[k] = ld_rlx4(sc->mod + 4 * (k < 3 ? t128 + 128 * k : i3));
#pragma unroll
          for (int k = 0; k < 4; k++) {
            v[k].x ^= tag16; v[k].y ^= tag16; v[k].z ^= tag16; v[k].w ^= tag16;
            bad |= v[k].x | v[k].y | v[k].z | v[k].w;
          }
          if (!any(bad & 0xffffu) || ++it > SPIN_MAX) break;
        }
#pragma unroll
        for (int k = 0; k < 4; k++) sts4(sbase + O_MOD + 16 * (k < 3 ? t128 + 128 * k : i3), v[k].x, v[k].y, v[k].z, v[k].w);
      }
      CK(14);
      bar_sync(10, NTHR);
      mbar_wait(full0 + 8 * B_Z2, 0);
      if (elect()) {
        load_a1(wp - 8, wp - 8);
        if (wp > 8 && wp - 8 < NG1) prefetch_l2(reinterpret_cast<const uint8_t*>(p.w1) + (size_t)(128 * (4 * ((wp - 8) >> 1) + (cta >> 5)) + 64 * (wp & 1) + 2 * (cta & 31)) * (2 * F_), 4 * F_);
      }
      __syncwarp();
    } else {
      const uint4 e0 = lds4(sbase + O_ST + 15360 + tid * 16), e1 = lds4(sbase + O_ST + 19456 + tid * 16), e2 = lds4(sbase + O_ST + 23552 + tid * 16);
      const uint32_t li[9] = {e0.x, e0.y, e0.z, e0.w, e1.x, e1.y, e1.z, e1.w, e2.x}, lx = e2.y, sb3 = e2.z;
      if (MODPOS == 0) bar_arrive(10, NTHR);
      CK(14);
      if (wp == 1) {
        const uint32_t* zu = upin(zin);
        if (elect()) mbar_expect(full0 + 8 * B_Z2, 19200);
        wait_cnt(sc->cnt + C_Z2, 120 * ep);
        if (elect()) {
          bulk_ld(sbase + O_IN, zu, 19200, full0 + 8 * B_Z2);
          TS(14);
        }
        __syncwarp();
      }
      if (MODPOS) { bar_sync(10, NTHR); load_mod3(MODPOS - 1); }
      mbar_wait(full0 + 8 * B_Z2, 0);
      CK(15);
      if (tid == 0) TS(11);
      uint2 v[10];
#pragma unroll
      for (int k1 = 0; k1 < 10; k1++) v[k1] = lds2(k1 < 9 ? li[k1] : lx);
      auto bad3 = [&]() {
        return any(or3(or3(diff2(v[0].x, v[1].x, tag1), diff2(v[2].x, v[3].x, tag1), diff2(v[4].x, v[5].x, tag1)), diff2(v[6].x, v[7].x, tag1), diff2(v[8].x, v[9].x, tag1)) & 1);
      };
      if (__builtin_expect(bad3(), 0)) {
        FAILCNT(1);
        int it = 0;
        do {
#pragma unroll
          for (int k1 = 0; k1 < 10; k1++) v[k1] = ld_rlx2(reinterpret_cast<const uint8_t*>(zin) + ((k1 < 9 ? li[k1] : lx) - (sbase + O_IN)));
        } while (bad3() && ++it < SPIN_MAX);
      }
      float2 za[9], zb[9];
#pragma unroll
      for (int i = 0; i < 9; i++) { za[i] = make_float2(bf_lo(v[i].x), bf_hi(v[i].x)); zb[i] = make_float2(bf_lo(v[i].y), bf_hi(v[i].y)); }
      if ((wp & 3) == wg) {
        const float sp = g ? 0.f : 1.f;
#pragma unroll
        for (int k = 1; k < 5; k++) {
          float2 a = za[k], b = za[9 - k];
          za[k] = make_float2(fmaf(-sp, b.x, a.x), fmaf(sp, b.y, a.y)); za[9 - k] = make_float2(fmaf(sp, a.x, b.x), fmaf(-sp, a.y, b.y));
          a = zb[k]; b = zb[9 - k];
          zb[k] = make_float2(fmaf(-sp, b.x, a.x), fmaf(sp, b.y, a.y)); zb[9 - k] = make_float2(fmaf(sp, a.x, b.x), fmaf(-sp, a.y, b.y));
        }
        za[0].y = g ? za[0].y : bf_lo(v[9].x); zb[0].y = g ? zb[0].y : bf_lo(v[9].y);
      }
      dft9(za); dft9(zb);
#pragma unroll
      for (int n = 0; n < 8; n += 2) {
        const int i0 = (9 - n) % 9, i1 = 8 - n;
        stmatrix4(sb3 + n * 2048, pack_bf16(za[i0].x, zb[i0].x), pack_bf16(za[i0].y, zb[i0].y), pack_bf16(za[i1].x, zb[i1].x), pack_bf16(za[i1].y, zb[i1].y));
      }
      stmatrix2(sb3 + 8 * 2048, pack_bf16(za[1].x, zb[1].x), pack_bf16(za[1].y, zb[1].y));
      fence_async_smem();
    }
    CK(16);
    __syncthreads();
    CK(17);
    float acc[24];
    const uint32_t db = (((sbase + O_B3 + wg * 6144) & 0x3FFFF) >> 4) | ((128 >> 4) << 16);
    wg_fence();
#pragma unroll
    for (int kk = 0; kk < 4; kk++) wgmma_rs_48(acc, af[kk].x, af[kk].y, af[kk].z, af[kk].w, db + kk * 16, 1024 >> 4, kk);
    wg_commit();
    if (wg < 2 && MODPOS == 0) load_mod3(0);
    wg_wait<0>();
    reg_fence(acc);
    CK(18);
#pragma unroll
    for (int i = 0; i < 3; i++) {
      const float* a = &acc[8 * i];
      const uint32_t a0 = pack_bf16(a[0], a[1]), a1 = pack_bf16(a[2], a[3]), a2 = pack_bf16(a[4], a[5]), a3 = pack_bf16(a[6], a[7]);
#pragma unroll
      for (int jh = 0; jh < 2; jh++) {
        float y[4];
        mma16<false>(y, a0, a1, a2, a3, tc[2 * jh], tc[2 * jh + 1]);
        sts(sy[2 * i] + jh * (4 * 584 * 4), pack_bf16(y[0], y[1]));
        sts(sy[2 * i + 1] + jh * (4 * 584 * 4), pack_bf16(y[2], y[3]));
      }
    }
    CK(19);
    if (wg == 2) { bar_arrive(7, NTHR); bar_sync(15, NB15); }
    else {
      bar_sync(7, NTHR);
      if ((LNM >> wp) & 1) bar_sync(15, NB15);
      CK(20);
      float a[18], b[18];
#pragma unroll
      for (int i = 0; i < 9; i++) {
        const uint2 y = lds2(syl + 256 * i);
        xr[i] = hfma2(ga[i], __byte_perm(y.x, y.y, 0x5410), xr[i]);
        xr[9 + i] = hfma2(ga[i], __byte_perm(y.x, y.y, 0x7632), xr[9 + i]);
        a[2 * i] = bf_lo(xr[i]); a[2 * i + 1] = bf_hi(xr[i]); b[2 * i] = bf_lo(xr[9 + i]); b[2 * i + 1] = bf_hi(xr[9 + i]);
      }
      float oa, ra, ob, rb;
      if (MODPOS == 2) load_mod3(2);
      ln_stats2(a, b, 1.0f, oa, ra, ob, rb);
      CK(21);
#pragma unroll
      for (int i = 0; i < 9; i++) {
        const float c0 = __uint_as_float(sw[i].x), c1 = __uint_as_float(sw[i].y), s0 = __uint_as_float(sh[i].x), s1 = __uint_as_float(sh[i].y);
        a[2 * i] = fmaf(fmaf(a[2 * i], ra, oa), c0, s0); a[2 * i + 1] = fmaf(fmaf(a[2 * i + 1], ra, oa), c1, s1);
        b[2 * i] = fmaf(fmaf(b[2 * i], rb, ob), c0, s0); b[2 * i + 1] = fmaf(fmaf(b[2 * i + 1], rb, ob), c1, s1);
      }
      ln_stats2(a, b, 0.5f, oa, ra, ob, rb);
      CK(22);
      if (wp < 2) bar_arrive(15, NB15);
      uint32_t hv[18];
#pragma unroll
      for (int i = 0; i < 9; i++) {
        const int k = i == 2 ? 1 : i == 6 ? 2 : 0;
        hv[2 * i] = bitsel(pack_bf16(fmaf(a[2 * i], ra, oa), fmaf(a[2 * i + 1], ra, oa)), ham[k], tag1);
        hv[2 * i + 1] = bitsel(pack_bf16(fmaf(b[2 * i], rb, ob), fmaf(b[2 * i + 1], rb, ob)), ham[k], tag1);
      }
      if (wp < 2) {
#pragma unroll
        for (int i = 0; i < 18; i++) {
          const int k = (i >> 1) == 2 ? 1 : (i >> 1) == 6 ? 2 : 0;
          asm volatile("st.global.b32 [%0], %1;" ::"l"(h3g + sh3[k] + (i >> 1) * 8192 + (i & 1) * 64), "r"(hv[i]) : "memory");
        }
        if (elect()) red_add(sc->cnt + C_H3 + (cta >> 4), 1);
        if (tid == 0) TS(13);
      } else {
#pragma unroll
        for (int i = 0; i < 18; i++) sts(sh3[(i >> 1) == 2 ? 1 : (i >> 1) == 6 ? 2 : 0] + (i >> 1) * 512 + (i & 1) * 64, hv[i]);
        fence_async_smem();
      }
      bar_arrive(9, 288);
      CK(23);
    }
  }

  const bool g2 = rows;
  const int z2 = cta, r = z2 >> 6;
  const int s2 = 128 * ((z2 >> 2) & 15), d2 = 144 * (z2 & 3);
  constexpr int ST0 = (32 - JSK - 1) % NST, ST1 = 31 % NST;

  if (wg == 2) {
    asm volatile("setmaxnreg.dec.sync.aligned.u32 40;");
    auto load_b = [&](bool second, int i, int st) {
      const uint32_t lb = full0 + 8 * (B_LAND + st), bytes = second ? 18432 : STAGE - a1bytes;
      mbar_expect(lb, bytes);
      bulk_ld(sbase + (second ? st * STAGE2 + 16384 : st * STAGE + a1bytes),
              second ? sc->u + ((size_t)(36 * r + kb2_order(i)) * D_ + d2) * 128 : sc->h3 + ((size_t)(i * 18 + (d1 >> 5)) << 12), bytes, lb);
    };
    if (wp == 8) {
      int st = rows ? 4 : 0, ph = 1;
#pragma unroll 1
      for (int kb = st; kb < 32; kb++) {
        if (rows && (kb >> 1) == 2) mbar_wait(full0 + 8 * (B_S4 - 4 + kb), 0);
        mbar_wait(empty0 + 8 * st, ph);
        if (elect()) {
          load_a1(st, kb);
          if (kb >= PF2K && kb < PF2K + PF2 && g2)
            prefetch_l2(reinterpret_cast<const uint8_t*>(p.w2) + (size_t)(36 * r + kb2_order(kb - PF2K)) * 262144 + (z2 & 63) * 4096, 4096);
        }
        __syncwarp();
        ring_next<false>(st, ph);
      }
      if (g2) {
        st++;
#pragma unroll 1
        for (int i = 0; i < 36; i++) {
          if (i == HOLDA) mbar_wait(full0 + 8 * B_GO, 0);
          mbar_wait(empty0 + 8 * st, ph);
          if (elect()) {
            mbar_expect(full0 + 8 * st, 16384);
            tma3d_ef(sbase + st * STAGE2, &maps.w2, 64 * (36 * r + kb2_order(i)), s2 >> 6, full0 + 8 * st);
          }
          __syncwarp();
          ring_next<true>(st, ph);
        }
      }
    } else if (wp >= 10) {
      const int sw = wp - 10;
      if (sw) {
        if (rows) {
          bar_sync(9, 288);
          mbar_wait(full0 + 8 * H3W, 0);
          if (elect()) { tma_st3d(&maps.h3, sbase + O_B3 + 4608, 64 * (cta & 15), 18 * (cta >> 4), 1); mbar_arrive(full0 + 8 * B_S4); }
          bulk_commit_wait();
          if (elect()) {
            red_add(sc->cnt + C_H3 + (cta >> 4) + 8, 2);
            mbar_arrive(full0 + 8 * B_S5); mbar_arrive(full0 + 8 * B_S5);
            TS(24);
            asm volatile("fence.acq_rel.gpu;" ::: "memory");
            red_add(&sc->cnt[C_X + 64], 1);
          }
          __syncwarp();
        }
        if (g2) {
          uint2 v[3];
          int it = 0;
          do {
#pragma unroll
            for (int i = 0; i < 3; i++) v[i] = ld_rlx2(sc->mod + 3 * D_ + d2 + 2 * min(l + 32 * i, 71));
          } while (any(or3(diff2(v[0].x, v[0].y, tag16), diff2(v[1].x, v[1].y, tag16), diff2(v[2].x, v[2].y, tag16)) & 0xffffu) && ++it < SPIN_MAX);
#pragma unroll
          for (int i = 0; i < 3; i++) sts(sbase + O_GB + 4 * min(l + 32 * i, 71), __byte_perm(v[i].x, v[i].y, 0x7632));
          __syncwarp();
        }
        wait_cnt<true>(&sc->cnt[C_X + 64], 128 * ep);
        if (elect()) mbar_arrive(full0 + 8 * B_X);
        __syncwarp();
      }
      uint32_t lph = 0;
      auto check_tiles = [&](bool second, int n, int st, uint32_t o1, uint32_t d2nd) {
        const uint32_t b1 = pin(sbase + o1), b2 = pin(sbase + o1 + d2nd);
        int i = 0, it = 0;
#pragma unroll 1
        do {
          const uint32_t so = st * (second ? STAGE2 : STAGE);
          mbar_wait(full0 + 8 * (B_LAND + st), (lph >> st) & 1);
          lph ^= 1u << st;
          uint32_t v[20];
#pragma unroll
          for (int k = 0; k < 20; k++) if (!second || k < 10 || k >= 12) v[k] = lds(k < 12 ? b1 + so + k * 1024 : b2 + so + (k - 12) * 1024); else v[k] = tag1;
#pragma unroll
          for (int k = 0; k < 10; k++) v[k] = diff2(v[2 * k], v[2 * k + 1], tag1);
          const uint32_t bad = or3(or3(or3(v[0], v[1], v[2]), or3(v[3], v[4], v[5]), v[6]), v[7], or3(v[8], v[9], 0));
          if (__builtin_expect(any(bad & 1) && ++it < SPIN_MAX, 0)) {
            FAILCNT(2 + second);
            fence_async_smem();
            __syncwarp();
            if (elect()) load_b(second, i, st);
            __syncwarp();
            continue;
          }
          if (elect()) mbar_arrive(full0 + 8 * st);
          if (++st == NST) st = 0;
          i++;
        } while (i < n);
      };
      if (!sw) check_tiles(false, NV1, 0, a1bytes + l * 32 + (l >> 2) * 4, helper ? 4096 : 12288);
      const bool first = helper || m1 < W0N;
#pragma unroll 1
      for (int k = sw ? first : !first; k <= sw; k++) {
        const uint32_t stg = sbase + (!k ? ST0 * STAGE : helper ? ST1 * STAGE : O_U1);
        const int kbA = (f1 >> 6) + (helper ? 2 : 1) * (k ^ flip), kbB = helper ? (f1 >> 6) + 1 : kbA;
        uint8_t* const uA = upin(sc->u + ((size_t)kbA * D_ + d1) * 128);
        uint8_t* const uB = upin(sc->u + ((size_t)kbB * D_ + (helper ? d1 : d1 + 96)) * 128);
        unsigned* const fA = pin(sc->cnt + C_U + kb2_pos(kbA));
        unsigned* const fB = pin(sc->cnt + C_U + kb2_pos(kbB));
        const bool slow = sw && !helper;
        bar_sync(11 + k, 160);
        if (!slow) { if (elect()) { bulk_st(uA, stg, 96 * 128); TS(k ? 31 : 30); } __syncwarp(); }
        bar_sync(13 + k, 160);
        if (slow) {
          if (g2) mbar_wait(full0 + 8 * B_GO, 0);
          if (first) pause(10 * TRK0);
#pragma unroll 1
          for (int i = 0; i < 20480; i += 2048) {
            if (elect()) bulk_st(uA + i, stg + i, 2048);
            pause(k ? TRKC : TRK0);
          }
        }
        if ((helper ? k : !slow) && elect()) bulk_st(uB, stg + 96 * 128, helper ? 96 * 128 : 64 * 128);
        bulk_commit_wait();
        if (elect()) { red_add(fA, 1); if (helper && k) red_add(fB, 1); }
        if (elect()) {
          if (!k || helper) mbar_arrive(empty0 + 8 * (k ? ST1 : ST0));
          TS(k ? 23 : 17);
          mbar_arrive(full0 + 8 * B_S5);
        }
        __syncwarp();
      }
      if (sw) {
        mbar_wait(full0 + 8 * B_S5, rows);
        if (elect()) { asm volatile("fence.acq_rel.gpu;" ::: "memory"); red_add(&sc->cnt[C_X], 1); }
        __syncwarp();
      }
      if (g2) {
        if (!sw) check_tiles(true, NV2, 3, 16384 + l * 32 + (4 * (g & 1) + (g >> 1)) * 4, 10240);
        else {
          wait_cnt<true>(&sc->cnt[C_X], NCTA * ep);
          if (elect()) {
            mbar_arrive(full0 + 8 * B_X);
            if (cta == 0) sc->cnt[C_EP] = ep;
          }
          __syncwarp();
        }
      }
      __syncwarp();
    } else {
      uint32_t ready = 0;
      int st = 0, ph = 1;
#pragma unroll 1
      for (int kb = 0; kb < 32; kb++) {
        const uint8_t* src = upin(sc->h3 + ((size_t)(kb * 18 + (d1 >> 5)) << 12));
        const uint32_t dst = upin(sbase + st * STAGE + a1bytes), lb = full0 + 8 * ((kb < NV1 ? B_LAND : 0) + st);
        if (kb == NV1) { mbar_wait(full0 + 8 * B_X, 0); fence_async_glb(); ready = ~0u; }
        if (rows && (kb >> 1) == 2) mbar_wait(full0 + 8 * (B_S4 - 4 + kb), 0);
        mbar_wait(empty0 + 8 * st, ph);
        if (elect()) mbar_expect(lb, STAGE - a1bytes);
        wait_flags(sc->cnt + C_H3 + l, (kb & 7) + (kb < 8 ? 0 : 8), 32 * ep, ready);
        if (elect()) bulk_ld(dst, src, STAGE - a1bytes, lb);
        ring_next<false>(st, ph);
      }
      if (g2) {
        ready = 0;
        st++;
#pragma unroll 1
        for (int i = 0; i < 36; i++) {
          const int kb = kb2_order(i);
          const uint8_t* src = upin(sc->u + ((size_t)(36 * r + kb) * D_ + d2) * 128);
          const uint32_t dst = upin(sbase + st * STAGE2 + 16384), lb = full0 + 8 * ((i < NV2 ? B_LAND : 0) + st);
          if (i == NV2) { mbar_wait(full0 + 8 * B_X, 1); fence_async_glb(); ready = ~0u; }
          mbar_wait(empty0 + 8 * st, ph);
          if (elect()) mbar_expect(lb, 18432);
          wait_flags(sc->cnt + C_U + 64 * r + l, i & 31, 4 * ep, ready);
          if (elect()) {
            bulk_ld(dst, src, 18432, lb);
            if (i == GOAT) mbar_arrive(full0 + 8 * B_GO);
          }
          ring_next<true>(st, ph);
        }
      }
    }
  } else {
    asm volatile("setmaxnreg.inc.sync.aligned.u32 232;");
    const int wgu = wg;
    constexpr uint32_t sb4 = sbase >> 4;
    const int w = wp & 3;
    Ring rg = {0, 0};
    uint32_t* const x1p = p.out + (size_t)(cta + 256 * wp) * 288 + l;
    const uint32_t ad = pin(sbase + (!wg ? ST0 * STAGE : helper ? ST1 * STAGE : O_U1) + (8 * (l >> 4) + (l & 7)) * 128 + (((2 * w + ((l >> 3) & 1)) ^ (l & 7)) << 4));
    const uint32_t uam = pin(g == 2 * t ? 0xfffefffeu : ~0u), uom = tag1 * 0x10001u;
    float acc[96];
    constexpr uint32_t LA = (8192 >> 4) << 16, LB = (4096 >> 4) << 16;
    {
      const int fa = f1 + (helper ? 128 : 64) * (wg ^ flip) + 16 * w + g, fb = helper ? f1 + 64 + 16 * w + g : fa;
      const float a0 = 0.5f * __bfloat162float(p.b1[fa]), a1 = 0.5f * __bfloat162float(p.b1[fa + 8]);
      const float b0 = 0.5f * __bfloat162float(p.b1[fb]), b1 = 0.5f * __bfloat162float(p.b1[fb + 8]);
#pragma unroll
      for (int i = 0; i < 96; i++) acc[i] = i < 48 ? ((i & 2) ? a1 : a0) : ((i & 2) ? b1 : b0);
      reg_fence(acc);
    }
    if (!helper) gemm_main<0>(acc, sb4 + (wgu ^ flip) * 512 + LA, 0, sb4 + 1024 + LB, wgu, rg, rows, x1p, xr);
    else {
      float ac2[96];
#pragma unroll
      for (int i = 0; i < 96; i++) asm volatile("mov.b32 %0, %1;" : "=f"(ac2[i]) : "f"(acc[i]));
      gemm_main<1>(ac2, sb4 + (wgu ^ flip) * 1024 + LA, sb4 + 512 + LA, sb4 + 1536 + LB, wgu, rg, rows, x1p, xr);
#pragma unroll
      for (int i = 0; i < 96; i++) asm volatile("mov.b32 %0, %1;" : "=f"(acc[i]) : "f"(ac2[i]));
    }
    if (t128 == 0) { TS(wg ? 16 : 6); if (wg) TSC(5); }
    {
      float tp[2] = {0.f, 0.f};
#pragma unroll
      for (int j = 0; j < 12; j++) {
        const float* a = &acc[8 * j];
        const float k3 = j < 2 ? GK3 : fmaf(tp[j & 1], 0.0f, GK3);
        float o[8];
#pragma unroll
        for (int e = 0; e < 8; e++) {
          float z = a[e] * fmaf(a[e] * k3, a[e], GK1);
          asm("tanh.approx.f32 %0, %0;" : "+f"(z));
          if (e == GDEP) tp[j & 1] = z;
          o[e] = fmaf(a[e], z, a[e]);
        }
        stmatrix4t(ad + j * 2048, bitsel(pack_bf16(o[0], o[1]), uam, uom), pack_bf16(o[2], o[3]), bitsel(pack_bf16(o[4], o[5]), uam, uom), pack_bf16(o[6], o[7]));
        if (j == 5) {
          fence_async_smem();
          bar_arrive(11 + wgu, 160);
        }
        if ((j == 5 && helper && !wgu) || (j == 9 && !helper)) break;
      }
      fence_async_smem();
      bar_arrive(13 + wgu, 160);
      if (t128 == 0) TS(wg ? 29 : 28);
    }
    if (g2) {
      const int mb = wgu ^ r;
      const int odd = z2 & 1;
      uint4 gq[4];
      uint2 gs;
      {
        float a0 = 0.f, a1 = 0.f;
        if (wgu) { a0 = __bfloat162float(p.b2[s2 + 64 * mb + 16 * w + g]); a1 = __bfloat162float(p.b2[s2 + 64 * mb + 16 * w + 8 + g]); }
#pragma unroll
        for (int i = 0; i < 4; i++) gq[i] = lds4(sbase + O_GB + 32 * odd + 64 * i + 16 * t);
        gs = lds2(sbase + O_GB + (odd ? 0 : 256) + 8 * t);
#pragma unroll
        for (int i = 0; i < 72; i++) acc[i] = (i & 2) ? a1 : a0;
      }
      uint32_t* const ob = p.out + (size_t)(s2 + 64 * mb + 16 * w + g) * 288 + (d2 >> 1);
      uint32_t* const oq = pin(ob + 8 * odd + 4 * t);
      uint32_t* const os = pin(ob + (odd ? 0 : 64) + 2 * t);
      rg.st++;
      gemm_main<3>(acc, sb4 + mb * 512 + LA, 0, sb4 + 1024 + (1 << 16), wgu, rg, rows, x1p, xr);
      if (t128 == 0) { TS(wg ? 20 : 19); if (wg) TSC(22); }
      auto finish = [&](const float* aq, const float* as) {
#pragma unroll
        for (int i = 0; i < 8; i++) {
          const float* a = aq + 16 * (i >> 1) + 2 * (i & 1);
          const uint4 gv = gq[i >> 1];
          red_bf16x8(oq + (i & 1) * 2304 + 16 * (i >> 1), hmul2(gv.x, pack_bf16(a[0], a[1])), hmul2(gv.y, pack_bf16(a[4], a[5])),
                     hmul2(gv.z, pack_bf16(a[8], a[9])), hmul2(gv.w, pack_bf16(a[12], a[13])));
        }
#pragma unroll
        for (int i = 0; i < 2; i++) red_bf16x4(os + i * 2304, hmul2(gs.x, pack_bf16(as[2 * i], as[2 * i + 1])), hmul2(gs.y, pack_bf16(as[2 * i + 4], as[2 * i + 5])));
      };
      if (odd) finish(&acc[8], &acc[0]); else finish(&acc[0], &acc[64]);
      if (t128 == 0) TS(wg ? 7 : 21);
      __syncwarp();
    }
  }
}

typedef CUresult (*EncodeFn)(CUtensorMap*, CUtensorMapDataType, cuuint32_t, void*, const cuuint64_t*, const cuuint64_t*, const cuuint32_t*,
                             const cuuint32_t*, CUtensorMapInterleave, CUtensorMapSwizzle, CUtensorMapL2promotion, CUtensorMapFloatOOBfill);

struct Dim { cuuint64_t n, stride; cuuint32_t box; };
template <int RANK>
void make_map(EncodeFn enc, CUtensorMap* m, bool words, int swz, const void* ptr, const Dim (&d)[RANK]) {
  cuuint64_t gd[RANK], gs[RANK];
  cuuint32_t bx[RANK], es[RANK];
  for (int i = 0; i < RANK; i++) { gd[i] = d[i].n; gs[i] = d[i].stride; bx[i] = d[i].box; es[i] = 1; }
  enc(m, words ? CU_TENSOR_MAP_DATA_TYPE_UINT32 : CU_TENSOR_MAP_DATA_TYPE_BFLOAT16, RANK, const_cast<void*>(ptr), gd, gs + 1, bx, es,
      CU_TENSOR_MAP_INTERLEAVE_NONE, static_cast<CUtensorMapSwizzle>(swz),
      swz == 3 ? CU_TENSOR_MAP_L2_PROMOTION_L2_256B : CU_TENSOR_MAP_L2_PROMOTION_NONE, CU_TENSOR_MAP_FLOAT_OOB_FILL_NONE);
}

}

extern "C" void kernel_launch(void* const* d_in, const int* in_sizes, int n_in, void* d_out, int out_size) {
  (void)in_sizes; (void)n_in; (void)out_size;
  static EncodeFn enc = nullptr;
  static void *sptr = nullptr, *tptr = nullptr;
  if (!enc) {
    void* f = nullptr; cudaDriverEntryPointQueryResult qr;
    cudaGetDriverEntryPoint("cuTensorMapEncodeTiled", &f, cudaEnableDefault, &qr);
    enc = reinterpret_cast<EncodeFn>(f);
    cudaFuncSetAttribute(fused_kernel, cudaFuncAttributeMaxDynamicSharedMemorySize, SMEM_BYTES);
    cudaGetSymbolAddress(&sptr, g_s);
    cudaGetSymbolAddress(&tptr, T_TAB);
  }
  Params p;
  p.x = (const __nv_bfloat16*)d_in[0]; p.wr = (const __nv_bfloat16*)d_in[1]; p.wi = (const __nv_bfloat16*)d_in[2];
  p.b1 = (const __nv_bfloat16*)d_in[5]; p.b2 = (const __nv_bfloat16*)d_in[7];
  p.c = (const __nv_bfloat16*)d_in[8]; p.wmod = (const __nv_bfloat16*)d_in[9];
  p.w1 = (const __nv_bfloat16*)d_in[4]; p.w2 = (const __nv_bfloat16*)d_in[6];
  p.out = static_cast<uint32_t*>(d_out); p.s = static_cast<Scratch*>(sptr); p.tab = static_cast<const uint4*>(tptr);
  Maps maps;
  make_map<4>(enc, &maps.w1a, false, 3, p.w1, {{64, 0, 64}, {16, 128 * 2 * F_, 4}, {128, 2 * F_, 16}, {72, 128, 2}});
  make_map<4>(enc, &maps.w1b, false, 3, p.w1, {{64, 0, 64}, {16, 128 * 2 * F_, 4}, {128, 2 * F_, 16}, {72, 128, 3}});
  make_map<3>(enc, &maps.w2, false, 3, p.w2, {{64, 0, 64}, {F_, 2 * S_, 64}, {32, 128, 2}});
  make_map<2>(enc, &maps.z1, true, 0, p.s->z1, {{5120, 0, 40}, {120, 20480, 60}});
  for (int i = 0; i < 2; i++) make_map<2>(enc, &maps.z2[i], true, 0, p.s->z2, {{4800, 0, i ? 16u : 24u}, {128, 19200, 128}});
  for (int i = 0; i < 4; i++) make_map<2>(enc, &maps.wf[i], false, 2 - (i & 1), (i & 2) ? p.wi : p.wr, {{16 * DF_, 0, (i & 1) ? 16u : 32u}, {128, 32 * DF_, 128}});
  make_map<2>(enc, &maps.wm, false, 1, p.wmod, {{6 * D_, 0, 16}, {D_, 12 * D_, 192}});
  make_map<3>(enc, &maps.h3, true, 0, p.s->h3, {{1024, 0, 64}, {144, 4096, 18}, {4, 144 * 4096, 3}});
  fused_kernel<<<NCTA, NTHR, SMEM_BYTES, cudaStreamPerThread>>>(p, maps);
}
```

```cpp
#include <cuda_runtime.h>
#include <cuda_bf16.h>
#include <cuda.h>
#include <stdint.h>

namespace {

constexpr int S_ = 2048, D_ = 576, DF_ = 289, F_ = 4608;
constexpr int NCTA = 132, NTHR = 384;
constexpr int STAGE = 36864, NST = 6;
constexpr int STAGE2 = 34816, O_U1 = NST * STAGE2, O_GB = O_U1 + 20480, SMEM_BYTES = 232448;
constexpr uint32_t sbase = 1024, red = sbase + NST * STAGE, full0 = sbase + SMEM_BYTES - 256, empty0 = full0 + 8 * NST;
constexpr int O_NRM = 0, O_B1 = 19456, O_Z1 = 38912, O_P2 = 59392, O_ST = 3 * STAGE;
constexpr int O_RAW = 4 * STAGE;
constexpr int O_IN = 4 * STAGE, O_Y = O_IN + 19456, O_B3 = O_IN + 38912, O_MOD = O_IN + 57344;

__device__ __align__(128) const uint32_t T_TAB[5632] = {
0x3f803f80,0xbf803f80,0x3f803f80,0xbf803f80,0x3f803f80,0xbf803f80,0x3f803f80,0xbf803f80,0x3f803f80,0xbf803f80,0x3f803f80,0xbf803f80,
0x3f803f80,0xbf803f80,0x3f803f80,0xbf803f80,0x3f7f3f80,0xbdc90000,0x3f223f35,0xbf46bf35,0x3f753f7b,0xbe95be48,0x3ef13f0e,0xbf62bf55,
0x3f623f6d,0xbef1bec4,0x3e953ec4,0xbf75bf6d,0x3f463f55,0xbf22bf0e,0x3dc93e48,0xbf7fbf7b,0x3f7b3f80,0xbe480000,0xbe480000,0xbf7bbf80,
0x3f553f6d,0xbf0ebec4,0xbf0ebec4,0xbf55bf6d,0x3f0e3f35,0xbf55bf35,0xbf55bf35,0xbf0ebf35,0x3e483ec4,0xbf7bbf6d,0xbf7bbf6d,0xbe48bec4,
0x3f753f80,0xbe950000,0xbf62bf35,0xbef1bf35,0x3f223f55,0xbf46bf0e,0xbf7fbf7b,0x3dc9be48,0x3dc93ec4,0xbf7fbf6d,0xbf46bf6d,0x3f223ec4,
0xbef1be48,0xbf62bf7b,0xbe95bf0e,0x3f753f55,0x3f6d3f80,0xbec40000,0xbf6dbf80,0x3ec40000,0x3ec43f35,0xbf6dbf35,0xbec4bf35,0x3f6d3f35,
0xbec40000,0xbf6dbf80,0x3ec40000,0x3f6d3f80,0xbf6dbf35,0xbec4bf35,0x3f6d3f35,0x3ec43f35,0x3f623f80,0xbef10000,0xbe95bf35,0x3f753f35,
0x3dc93f0e,0xbf7fbf55,0x3f223e48,0x3f463f7b,0xbf46bec4,0xbf22bf6d,0x3f7f3f6d,0xbdc93ec4,0xbf75bf7b,0x3e95be48,0x3ef13f55,0xbf62bf0e,
0x3f553f80,0xbf0e0000,0x3f0e0000,0x3f553f80,0xbe483ec4,0xbf7bbf6d,0x3f7b3f6d,0xbe483ec4,0xbf7bbf35,0xbe48bf35,0x3e483f35,0xbf7bbf35,
0xbf0ebf6d,0x3f553ec4,0xbf55bec4,0xbf0ebf6d,0x3f463f80,0xbf220000,0x3f7f3f35,0x3dc93f35,0xbef13e48,0xbf62bf7b,0x3e953f55,0xbf75bf0e,
0xbf75bf6d,0x3e95bec4,0xbf62bec4,0xbef1bf6d,0x3dc9bf0e,0x3f7f3f55,0xbf22bf7b,0x3f463e48,0x3f353f80,0xbf350000,0x3f353f80,0xbf350000,
0xbf350000,0xbf35bf80,0xbf350000,0xbf35bf80,0xbf35bf80,0x3f350000,0xbf35bf80,0x3f350000,0x3f350000,0x3f353f80,0x3f350000,0x3f353f80,
0x3f223f80,0xbf460000,0xbdc93f35,0xbf7fbf35,0xbf62be48,0xbef1bf7b,0xbf75bf55,0x3e95bf0e,0xbe95bf6d,0x3f753ec4,0x3ef1bec4,0x3f623f6d,
0x3f7f3f0e,0x3dc93f55,0x3f463f7b,0xbf223e48,0x3f0e3f80,0xbf550000,0xbf550000,0xbf0ebf80,0xbf7bbec4,0xbe48bf6d,0xbe48bf6d,0x3f7b3ec4,
0x3e48bf35,0x3f7b3f35,0x3f7b3f35,0xbe483f35,0x3f553f6d,0xbf0e3ec4,0xbf0e3ec4,0xbf55bf6d,0x3ef13f80,0xbf620000,0xbf75bf35,0x3e95bf35,
0xbf7fbf0e,0x3dc9bf55,0x3f46be48,0x3f223f7b,0x3f22bec4,0x3f463f6d,0x3dc93f6d,0xbf7fbec4,0x3e953f7b,0xbf75be48,0xbf62bf55,0x3ef1bf0e,
0x3ec43f80,0xbf6d0000,0xbec4bf80,0x3f6d0000,0xbf6dbf35,0x3ec4bf35,0x3f6d3f35,0xbec43f35,0x3f6d0000,0x3ec43f80,0xbf6d0000,0xbec4bf80,
0xbec43f35,0xbf6dbf35,0x3ec4bf35,0x3f6d3f35,0x3e953f80,0xbf750000,0x3ef1bf35,0x3f623f35,0xbf46bf55,0x3f22bf0e,0x3dc93f7b,0xbf7fbe48,
0x3f7f3ec4,0xbdc93f6d,0xbf22bf6d,0x3f46bec4,0xbf623e48,0xbef1bf7b,0x3f753f0e,0xbe953f55,0x3e483f80,0xbf7b0000,0x3f7b0000,0x3e483f80,
0xbf0ebf6d,0x3f55bec4,0xbf553ec4,0xbf0ebf6d,0x3f553f35,0xbf0e3f35,0x3f0ebf35,0x3f553f35,0xbf7bbec4,0x3e48bf6d,0xbe483f6d,0xbf7bbec4,
0x3dc93f80,0xbf7f0000,0x3f463f35,0xbf223f35,0xbe95bf7b,0x3f75be48,0xbf62bf0e,0x3ef1bf55,0x3ef13f6d,0xbf623ec4,0x3f753ec4,0xbe953f6d,
0xbf22bf55,0x3f46bf0e,0xbf7fbe48,0x3dc9bf7b,0x3f80,0xbf800000,0x3f80,0xbf800000,0xbf80,0x3f800000,0xbf80,0x3f800000,
0x3f80,0xbf800000,0x3f80,0xbf800000,0xbf80,0x3f800000,0xbf80,0x3f800000,0xbdc93f80,0xbf7f0000,0xbf463f35,0xbf22bf35,
0x3e95bf7b,0x3f753e48,0x3f62bf0e,0x3ef13f55,0xbef13f6d,0xbf62bec4,0xbf753ec4,0xbe95bf6d,0x3f22bf55,0x3f463f0e,0x3f7fbe48,0x3dc93f7b,
0xbe483f80,0xbf7b0000,0xbf7b0000,0x3e48bf80,0x3f0ebf6d,0x3f553ec4,0x3f553ec4,0xbf0e3f6d,0xbf553f35,0xbf0ebf35,0xbf0ebf35,0x3f55bf35,
0x3f7bbec4,0x3e483f6d,0x3e483f6d,0xbf7b3ec4,0xbe953f80,0xbf750000,0xbef1bf35,0x3f62bf35,0x3f46bf55,0x3f223f0e,0xbdc93f7b,0xbf7f3e48,
0xbf7f3ec4,0xbdc9bf6d,0x3f22bf6d,0x3f463ec4,0x3f623e48,0xbef13f7b,0xbf753f0e,0xbe95bf55,0xbec43f80,0xbf6d0000,0x3ec4bf80,0x3f6d0000,
0x3f6dbf35,0x3ec43f35,0xbf6d3f35,0xbec4bf35,0xbf6d0000,0x3ec4bf80,0x3f6d0000,0xbec43f80,0x3ec43f35,0xbf6d3f35,0xbec4bf35,0x3f6dbf35,
0xbef13f80,0xbf620000,0x3f75bf35,0x3e953f35,0x3f7fbf0e,0x3dc93f55,0xbf46be48,0x3f22bf7b,0xbf22bec4,0x3f46bf6d,0xbdc93f6d,0xbf7f3ec4,
0xbe953f7b,0xbf753e48,0x3f62bf55,0x3ef13f0e,0xbf0e3f80,0xbf550000,0x3f550000,0xbf0e3f80,0x3f7bbec4,0xbe483f6d,0x3e48bf6d,0x3f7bbec4,
0xbe48bf35,0x3f7bbf35,0xbf7b3f35,0xbe48bf35,0xbf553f6d,0xbf0ebec4,0x3f0e3ec4,0xbf553f6d,0xbf223f80,0xbf460000,0x3dc93f35,0xbf7f3f35,
0x3f62be48,0xbef13f7b,0x3f75bf55,0x3e953f0e,0x3e95bf6d,0x3f75bec4,0xbef1bec4,0x3f62bf6d,0xbf7f3f0e,0x3dc9bf55,0xbf463f7b,0xbf22be48,
0xbf353f80,0xbf350000,0xbf353f80,0xbf350000,0x3f350000,0xbf353f80,0x3f350000,0xbf353f80,0x3f35bf80,0x3f350000,0x3f35bf80,0x3f350000,
0xbf350000,0x3f35bf80,0xbf350000,0x3f35bf80,0xbf463f80,0xbf220000,0xbf7f3f35,0x3dc9bf35,0x3ef13e48,0xbf623f7b,0xbe953f55,0xbf753f0e,
0x3f75bf6d,0x3e953ec4,0x3f62bec4,0xbef13f6d,0xbdc9bf0e,0x3f7fbf55,0x3f22bf7b,0x3f46be48,0xbf553f80,0xbf0e0000,0xbf0e0000,0x3f55bf80,
0x3e483ec4,0xbf7b3f6d,0xbf7b3f6d,0xbe48bec4,0x3f7bbf35,0xbe483f35,0xbe483f35,0xbf7b3f35,0x3f0ebf6d,0x3f55bec4,0x3f55bec4,0xbf0e3f6d,
0xbf623f80,0xbef10000,0x3e95bf35,0x3f75bf35,0xbdc93f0e,0xbf7f3f55,0xbf223e48,0x3f46bf7b,0x3f46bec4,0xbf223f6d,0xbf7f3f6d,0xbdc9bec4,
0x3f75bf7b,0x3e953e48,0xbef13f55,0xbf623f0e,0xbf6d3f80,0xbec40000,0x3f6dbf80,0x3ec40000,0xbec43f35,0xbf6d3f35,0x3ec4bf35,0x3f6dbf35,
0x3ec40000,0xbf6d3f80,0xbec40000,0x3f6dbf80,0x3f6dbf35,0xbec43f35,0xbf6d3f35,0x3ec4bf35,0xbf753f80,0xbe950000,0x3f62bf35,0xbef13f35,
0xbf223f55,0xbf463f0e,0x3f7fbf7b,0x3dc93e48,0xbdc93ec4,0xbf7f3f6d,0x3f46bf6d,0x3f22bec4,0x3ef1be48,0xbf623f7b,0x3e95bf0e,0x3f75bf55,
0xbf7b3f80,0xbe480000,0x3e480000,0xbf7b3f80,0xbf553f6d,0xbf0e3ec4,0x3f0ebec4,0xbf553f6d,0xbf0e3f35,0xbf553f35,0x3f55bf35,0xbf0e3f35,
0xbe483ec4,0xbf7b3f6d,0x3f7bbf6d,0xbe483ec4,0xbf7f3f80,0xbdc90000,0xbf223f35,0xbf463f35,0xbf753f7b,0xbe953e48,0xbef13f0e,0xbf623f55,
0xbf623f6d,0xbef13ec4,0xbe953ec4,0xbf753f6d,0xbf463f55,0xbf223f0e,0xbdc93e48,0xbf7f3f7b,0x3f803f80,0xbf803f80,0x3f803f80,0xbf803f80,
0x3f803f80,0xbf803f80,0x3f803f80,0xbf803f80,0x3f803f80,0xbf803f80,0x3f803f80,0xbf803f80,0x3f803f80,0xbf803f80,0x3f803f80,0xbf803f80,
0xbdc90000,0xbf7fbf80,0xbf46bf35,0xbf22bf35,0xbe95be48,0xbf75bf7b,0xbf62bf55,0xbef1bf0e,0xbef1bec4,0xbf62bf6d,0xbf75bf6d,0xbe95bec4,
0xbf22bf0e,0xbf46bf55,0xbf7fbf7b,0xbdc9be48,0xbf7bbf80,0x3e480000,0x3e480000,0x3f7b3f80,0xbf55bf6d,0x3f0e3ec4,0x3f0e3ec4,0x3f553f6d,
0xbf0ebf35,0x3f553f35,0x3f553f35,0x3f0e3f35,0xbe48bec4,0x3f7b3f6d,0x3f7b3f6d,0x3e483ec4,0x3e950000,0x3f753f80,0x3ef13f35,0xbf62bf35,
0x3f463f0e,0x3f223f55,0xbdc93e48,0xbf7fbf7b,0x3f7f3f6d,0x3dc93ec4,0xbf22bec4,0xbf46bf6d,0x3f623f7b,0xbef1be48,0xbf75bf55,0xbe95bf0e,
0x3f6d3f80,0xbec40000,0xbf6dbf80,0x3ec40000,0x3ec43f35,0xbf6dbf35,0xbec4bf35,0x3f6d3f35,0xbec40000,0xbf6dbf80,0x3ec40000,0x3f6d3f80,
0xbf6dbf35,0xbec4bf35,0x3f6d3f35,0x3ec43f35,0xbef10000,0xbf62bf80,0x3f753f35,0x3e953f35,0xbf7fbf55,0xbdc9bf0e,0x3f463f7b,0xbf22be48,
0xbf22bf6d,0x3f463ec4,0xbdc93ec4,0xbf7fbf6d,0x3e95be48,0x3f753f7b,0xbf62bf0e,0xbef1bf55,0xbf55bf80,0x3f0e0000,0xbf0e0000,0xbf55bf80,
0x3e48bec4,0x3f7b3f6d,0xbf7bbf6d,0x3e48bec4,0x3f7b3f35,0x3e483f35,0xbe48bf35,0x3f7b3f35,0x3f0e3f6d,0xbf55bec4,0x3f553ec4,0x3f0e3f6d,
0x3f220000,0x3f463f80,0xbdc9bf35,0x3f7f3f35,0x3f623f7b,0xbef13e48,0x3f753f0e,0x3e953f55,0xbe953ec4,0xbf75bf6d,0x3ef13f6d,0xbf62bec4,
0xbf7fbf55,0x3dc9bf0e,0xbf46be48,0xbf22bf7b,0x3f353f80,0xbf350000,0x3f353f80,0xbf350000,0xbf350000,0xbf35bf80,0xbf350000,0xbf35bf80,
0xbf35bf80,0x3f350000,0xbf35bf80,0x3f350000,0x3f350000,0x3f353f80,0x3f350000,0x3f353f80,0xbf460000,0xbf22bf80,0xbf7fbf35,0x3dc9bf35,
0xbef1bf7b,0x3f623e48,0x3e95bf0e,0x3f753f55,0x3f753ec4,0x3e953f6d,0x3f623f6d,0xbef13ec4,0x3dc93f55,0xbf7fbf0e,0xbf223e48,0xbf46bf7b,
0xbf0ebf80,0x3f550000,0x3f550000,0x3f0e3f80,0x3f7b3ec4,0x3e483f6d,0x3e483f6d,0xbf7bbec4,0xbe483f35,0xbf7bbf35,0xbf7bbf35,0x3e48bf35,
0xbf55bf6d,0x3f0ebec4,0x3f0ebec4,0x3f553f6d,0x3f620000,0x3ef13f80,0xbe953f35,0xbf75bf35,0xbdc93f55,0xbf7fbf0e,0xbf22bf7b,0x3f46be48,
0xbf46bf6d,0x3f22bec4,0x3f7f3ec4,0x3dc93f6d,0x3f753e48,0x3e953f7b,0xbef13f0e,0xbf62bf55,0x3ec43f80,0xbf6d0000,0xbec4bf80,0x3f6d0000,
0xbf6dbf35,0x3ec4bf35,0x3f6d3f35,0xbec43f35,0x3f6d0000,0x3ec43f80,0xbf6d0000,0xbec4bf80,0xbec43f35,0xbf6dbf35,0x3ec4bf35,0x3f6d3f35,
0xbf750000,0xbe95bf80,0x3f623f35,0xbef13f35,0x3f22bf0e,0x3f463f55,0xbf7fbe48,0xbdc9bf7b,0xbdc93f6d,0xbf7fbec4,0x3f46bec4,0x3f223f6d,
0xbef1bf7b,0x3f62be48,0xbe953f55,0xbf75bf0e,0xbe48bf80,0x3f7b0000,0xbf7b0000,0xbe48bf80,0x3f0e3f6d,0xbf553ec4,0x3f55bec4,0x3f0e3f6d,
0xbf55bf35,0x3f0ebf35,0xbf0e3f35,0xbf55bf35,0x3f7b3ec4,0xbe483f6d,0x3e48bf6d,0x3f7b3ec4,0x3f7f0000,0x3dc93f80,0x3f22bf35,0x3f463f35,
0xbf753e48,0xbe95bf7b,0xbef13f55,0xbf62bf0e,0x3f62bec4,0x3ef13f6d,0x3e95bf6d,0x3f753ec4,0xbf463f0e,0xbf22bf55,0xbdc93f7b,0xbf7fbe48,
0x3f80,0xbf800000,0x3f80,0xbf800000,0xbf80,0x3f800000,0xbf80,0x3f800000,0x3f80,0xbf800000,0x3f80,0xbf800000,
0xbf80,0x3f800000,0xbf80,0x3f800000,0xbf7f0000,0x3dc9bf80,0xbf22bf35,0x3f46bf35,0x3f753e48,0xbe953f7b,0x3ef13f55,0xbf623f0e,
0xbf62bec4,0x3ef1bf6d,0xbe95bf6d,0x3f75bec4,0x3f463f0e,0xbf223f55,0x3dc93f7b,0xbf7f3e48,0x3e48bf80,0x3f7b0000,0x3f7b0000,0xbe483f80,
0xbf0e3f6d,0xbf55bec4,0xbf55bec4,0x3f0ebf6d,0x3f55bf35,0x3f0e3f35,0x3f0e3f35,0xbf553f35,0xbf7b3ec4,0xbe48bf6d,0xbe48bf6d,0x3f7bbec4,
0x3f750000,0xbe953f80,0xbf623f35,0xbef1bf35,0xbf22bf0e,0x3f46bf55,0x3f7fbe48,0xbdc93f7b,0x3dc93f6d,0xbf7f3ec4,0xbf46bec4,0x3f22bf6d,
0x3ef1bf7b,0x3f623e48,0x3e953f55,0xbf753f0e,0xbec43f80,0xbf6d0000,0x3ec4bf80,0x3f6d0000,0x3f6dbf35,0x3ec43f35,0xbf6d3f35,0xbec4bf35,
0xbf6d0000,0x3ec4bf80,0x3f6d0000,0xbec43f80,0x3ec43f35,0xbf6d3f35,0xbec4bf35,0x3f6dbf35,0xbf620000,0x3ef1bf80,0x3e953f35,0xbf753f35,
0x3dc93f55,0xbf7f3f0e,0x3f22bf7b,0x3f463e48,0x3f46bf6d,0x3f223ec4,0xbf7f3ec4,0x3dc9bf6d,0xbf753e48,0x3e95bf7b,0x3ef13f0e,0xbf623f55,
0x3f0ebf80,0x3f550000,0xbf550000,0x3f0ebf80,0xbf7b3ec4,0x3e48bf6d,0xbe483f6d,0xbf7b3ec4,0x3e483f35,0xbf7b3f35,0x3f7bbf35,0x3e483f35,
0x3f55bf6d,0x3f0e3ec4,0xbf0ebec4,0x3f55bf6d,0x3f460000,0xbf223f80,0x3f7fbf35,0x3dc93f35,0x3ef1bf7b,0x3f62be48,0xbe95bf0e,0x3f75bf55,
0xbf753ec4,0x3e95bf6d,0xbf623f6d,0xbef1bec4,0xbdc93f55,0xbf7f3f0e,0x3f223e48,0xbf463f7b,0xbf353f80,0xbf350000,0xbf353f80,0xbf350000,
0x3f350000,0xbf353f80,0x3f350000,0xbf353f80,0x3f35bf80,0x3f350000,0x3f35bf80,0x3f350000,0xbf350000,0x3f35bf80,0xbf350000,0x3f35bf80,
0xbf220000,0x3f46bf80,0x3dc9bf35,0x3f7fbf35,0xbf623f7b,0xbef1be48,0xbf753f0e,0x3e95bf55,0x3e953ec4,0xbf753f6d,0xbef13f6d,0xbf623ec4,
0x3f7fbf55,0x3dc93f0e,0x3f46be48,0xbf223f7b,0x3f55bf80,0x3f0e0000,0x3f0e0000,0xbf553f80,0xbe48bec4,0x3f7bbf6d,0x3f7bbf6d,0x3e483ec4,
0xbf7b3f35,0x3e48bf35,0x3e48bf35,0x3f7bbf35,0xbf0e3f6d,0xbf553ec4,0xbf553ec4,0x3f0ebf6d,0x3ef10000,0xbf623f80,0xbf753f35,0x3e95bf35,
0x3f7fbf55,0xbdc93f0e,0xbf463f7b,0xbf223e48,0x3f22bf6d,0x3f46bec4,0x3dc93ec4,0xbf7f3f6d,0xbe95be48,0x3f75bf7b,0x3f62bf0e,0xbef13f55,
0xbf6d3f80,0xbec40000,0x3f6dbf80,0x3ec40000,0xbec43f35,0xbf6d3f35,0x3ec4bf35,0x3f6dbf35,0x3ec40000,0xbf6d3f80,0xbec40000,0x3f6dbf80,
0x3f6dbf35,0xbec43f35,0xbf6d3f35,0x3ec4bf35,0xbe950000,0x3f75bf80,0xbef13f35,0xbf623f35,0xbf463f0e,0x3f22bf55,0x3dc93e48,0xbf7f3f7b,
0xbf7f3f6d,0x3dc9bec4,0x3f22bec4,0xbf463f6d,0xbf623f7b,0xbef13e48,0x3f75bf55,0xbe953f0e,0x3f7bbf80,0x3e480000,0xbe480000,0x3f7bbf80,
0x3f55bf6d,0x3f0ebec4,0xbf0e3ec4,0x3f55bf6d,0x3f0ebf35,0x3f55bf35,0xbf553f35,0x3f0ebf35,0x3e48bec4,0x3f7bbf6d,0xbf7b3f6d,0x3e48bec4,
0x3dc90000,0xbf7f3f80,0x3f46bf35,0xbf223f35,0x3e95be48,0xbf753f7b,0x3f62bf55,0xbef13f0e,0x3ef1bec4,0xbf623f6d,0x3f75bf6d,0xbe953ec4,
0x3f22bf0e,0xbf463f55,0x3f7fbf7b,0xbdc93e48,0x3f803f80,0xbf803f80,0x3f803f80,0xbf803f80,0x3f803f80,0xbf803f80,0x3f803f80,0xbf803f80,
0x3f803f80,0xbf803f80,0x3f803f80,0xbf803f80,0x3f803f80,0xbf803f80,0x3f803f80,0xbf803f80,0xbf7fbf80,0x3dc90000,0xbf22bf35,0x3f463f35,
0xbf75bf7b,0x3e953e48,0xbef1bf0e,0x3f623f55,0xbf62bf6d,0x3ef13ec4,0xbe95bec4,0x3f753f6d,0xbf46bf55,0x3f223f0e,0xbdc9be48,0x3f7f3f7b,
0x3f7b3f80,0xbe480000,0xbe480000,0xbf7bbf80,0x3f553f6d,0xbf0ebec4,0xbf0ebec4,0xbf55bf6d,0x3f0e3f35,0xbf55bf35,0xbf55bf35,0xbf0ebf35,
0x3e483ec4,0xbf7bbf6d,0xbf7bbf6d,0xbe48bec4,0xbf75bf80,0x3e950000,0x3f623f35,0x3ef13f35,0xbf22bf55,0x3f463f0e,0x3f7f3f7b,0xbdc93e48,
0xbdc9bec4,0x3f7f3f6d,0x3f463f6d,0xbf22bec4,0x3ef13e48,0x3f623f7b,0x3e953f0e,0xbf75bf55,0x3f6d3f80,0xbec40000,0xbf6dbf80,0x3ec40000,
0x3ec43f35,0xbf6dbf35,0xbec4bf35,0x3f6d3f35,0xbec40000,0xbf6dbf80,0x3ec40000,0x3f6d3f80,0xbf6dbf35,0xbec4bf35,0x3f6d3f35,0x3ec43f35,
0xbf62bf80,0x3ef10000,0x3e953f35,0xbf75bf35,0xbdc9bf0e,0x3f7f3f55,0xbf22be48,0xbf46bf7b,0x3f463ec4,0x3f223f6d,0xbf7fbf6d,0x3dc9bec4,
0x3f753f7b,0xbe953e48,0xbef1bf55,0x3f623f0e,0x3f553f80,0xbf0e0000,0x3f0e0000,0x3f553f80,0xbe483ec4,0xbf7bbf6d,0x3f7b3f6d,0xbe483ec4,
0xbf7bbf35,0xbe48bf35,0x3e483f35,0xbf7bbf35,0xbf0ebf6d,0x3f553ec4,0xbf55bec4,0xbf0ebf6d,0xbf46bf80,0x3f220000,0xbf7fbf35,0xbdc9bf35,
0x3ef1be48,0x3f623f7b,0xbe95bf55,0x3f753f0e,0x3f753f6d,0xbe953ec4,0x3f623ec4,0x3ef13f6d,0xbdc93f0e,0xbf7fbf55,0x3f223f7b,0xbf46be48,
0x3f353f80,0xbf350000,0x3f353f80,0xbf350000,0xbf350000,0xbf35bf80,0xbf350000,0xbf35bf80,0xbf35bf80,0x3f350000,0xbf35bf80,0x3f350000,
0x3f350000,0x3f353f80,0x3f350000,0x3f353f80,0xbf22bf80,0x3f460000,0x3dc9bf35,0x3f7f3f35,0x3f623e48,0x3ef13f7b,0x3f753f55,0xbe953f0e,
0x3e953f6d,0xbf75bec4,0xbef13ec4,0xbf62bf6d,0xbf7fbf0e,0xbdc9bf55,0xbf46bf7b,0x3f22be48,0x3f0e3f80,0xbf550000,0xbf550000,0xbf0ebf80,
0xbf7bbec4,0xbe48bf6d,0xbe48bf6d,0x3f7b3ec4,0x3e48bf35,0x3f7b3f35,0x3f7b3f35,0xbe483f35,0x3f553f6d,0xbf0e3ec4,0xbf0e3ec4,0xbf55bf6d,
0xbef1bf80,0x3f620000,0x3f753f35,0xbe953f35,0x3f7f3f0e,0xbdc93f55,0xbf463e48,0xbf22bf7b,0xbf223ec4,0xbf46bf6d,0xbdc9bf6d,0x3f7f3ec4,
0xbe95bf7b,0x3f753e48,0x3f623f55,0xbef13f0e,0x3ec43f80,0xbf6d0000,0xbec4bf80,0x3f6d0000,0xbf6dbf35,0x3ec4bf35,0x3f6d3f35,0xbec43f35,
0x3f6d0000,0x3ec43f80,0xbf6d0000,0xbec4bf80,0xbec43f35,0xbf6dbf35,0x3ec4bf35,0x3f6d3f35,0xbe95bf80,0x3f750000,0xbef13f35,0xbf62bf35,
0x3f463f55,0xbf223f0e,0xbdc9bf7b,0x3f7f3e48,0xbf7fbec4,0x3dc9bf6d,0x3f223f6d,0xbf463ec4,0x3f62be48,0x3ef13f7b,0xbf75bf0e,0x3e95bf55,
0x3e483f80,0xbf7b0000,0x3f7b0000,0x3e483f80,0xbf0ebf6d,0x3f55bec4,0xbf553ec4,0xbf0ebf6d,0x3f553f35,0xbf0e3f35,0x3f0ebf35,0x3f553f35,
0xbf7bbec4,0x3e48bf6d,0xbe483f6d,0xbf7bbec4,0xbdc9bf80,0x3f7f0000,0xbf46bf35,0x3f22bf35,0x3e953f7b,0xbf753e48,0x3f623f0e,0xbef13f55,
0xbef1bf6d,0x3f62bec4,0xbf75bec4,0x3e95bf6d,0x3f223f55,0xbf463f0e,0x3f7f3e48,0xbdc93f7b,0x3f80,0xbf800000,0x3f80,0xbf800000,
0xbf80,0x3f800000,0xbf80,0x3f800000,0x3f80,0xbf800000,0x3f80,0xbf800000,0xbf80,0x3f800000,0xbf80,0x3f800000,
0x3dc9bf80,0x3f7f0000,0x3f46bf35,0x3f223f35,0xbe953f7b,0xbf75be48,0xbf623f0e,0xbef1bf55,0x3ef1bf6d,0x3f623ec4,0x3f75bec4,0x3e953f6d,
0xbf223f55,0xbf46bf0e,0xbf7f3e48,0xbdc9bf7b,0xbe483f80,0xbf7b0000,0xbf7b0000,0x3e48bf80,0x3f0ebf6d,0x3f553ec4,0x3f553ec4,0xbf0e3f6d,
0xbf553f35,0xbf0ebf35,0xbf0ebf35,0x3f55bf35,0x3f7bbec4,0x3e483f6d,0x3e483f6d,0xbf7b3ec4,0x3e95bf80,0x3f750000,0x3ef13f35,0xbf623f35,
0xbf463f55,0xbf22bf0e,0x3dc9bf7b,0x3f7fbe48,0x3f7fbec4,0x3dc93f6d,0xbf223f6d,0xbf46bec4,0xbf62be48,0x3ef1bf7b,0x3f75bf0e,0x3e953f55,
0xbec43f80,0xbf6d0000,0x3ec4bf80,0x3f6d0000,0x3f6dbf35,0x3ec43f35,0xbf6d3f35,0xbec4bf35,0xbf6d0000,0x3ec4bf80,0x3f6d0000,0xbec43f80,
0x3ec43f35,0xbf6d3f35,0xbec4bf35,0x3f6dbf35,0x3ef1bf80,0x3f620000,0xbf753f35,0xbe95bf35,0xbf7f3f0e,0xbdc9bf55,0x3f463e48,0xbf223f7b,
0x3f223ec4,0xbf463f6d,0x3dc9bf6d,0x3f7fbec4,0x3e95bf7b,0x3f75be48,0xbf623f55,0xbef1bf0e,0xbf0e3f80,0xbf550000,0x3f550000,0xbf0e3f80,
0x3f7bbec4,0xbe483f6d,0x3e48bf6d,0x3f7bbec4,0xbe48bf35,0x3f7bbf35,0xbf7b3f35,0xbe48bf35,0xbf553f6d,0xbf0ebec4,0x3f0e3ec4,0xbf553f6d,
0x3f22bf80,0x3f460000,0xbdc9bf35,0x3f7fbf35,0xbf623e48,0x3ef1bf7b,0xbf753f55,0xbe95bf0e,0xbe953f6d,0xbf753ec4,0x3ef13ec4,0xbf623f6d,
0x3f7fbf0e,0xbdc93f55,0x3f46bf7b,0x3f223e48,0xbf353f80,0xbf350000,0xbf353f80,0xbf350000,0x3f350000,0xbf353f80,0x3f350000,0xbf353f80,
0x3f35bf80,0x3f350000,0x3f35bf80,0x3f350000,0xbf350000,0x3f35bf80,0xbf350000,0x3f35bf80,0x3f46bf80,0x3f220000,0x3f7fbf35,0xbdc93f35,
0xbef1be48,0x3f62bf7b,0x3e95bf55,0x3f75bf0e,0xbf753f6d,0xbe95bec4,0xbf623ec4,0x3ef1bf6d,0x3dc93f0e,0xbf7f3f55,0xbf223f7b,0xbf463e48,
0xbf553f80,0xbf0e0000,0xbf0e0000,0x3f55bf80,0x3e483ec4,0xbf7b3f6d,0xbf7b3f6d,0xbe48bec4,0x3f7bbf35,0xbe483f35,0xbe483f35,0xbf7b3f35,
0x3f0ebf6d,0x3f55bec4,0x3f55bec4,0xbf0e3f6d,0x3f62bf80,0x3ef10000,0xbe953f35,0xbf753f35,0x3dc9bf0e,0x3f7fbf55,0x3f22be48,0xbf463f7b,
0xbf463ec4,0x3f22bf6d,0x3f7fbf6d,0x3dc93ec4,0xbf753f7b,0xbe95be48,0x3ef1bf55,0x3f62bf0e,0xbf6d3f80,0xbec40000,0x3f6dbf80,0x3ec40000,
0xbec43f35,0xbf6d3f35,0x3ec4bf35,0x3f6dbf35,0x3ec40000,0xbf6d3f80,0xbec40000,0x3f6dbf80,0x3f6dbf35,0xbec43f35,0xbf6d3f35,0x3ec4bf35,
0x3f75bf80,0x3e950000,0xbf623f35,0x3ef1bf35,0x3f22bf55,0x3f46bf0e,0xbf7f3f7b,0xbdc9be48,0x3dc9bec4,0x3f7fbf6d,0xbf463f6d,0xbf223ec4,
0xbef13e48,0x3f62bf7b,0xbe953f0e,0xbf753f55,0xbf7b3f80,0xbe480000,0x3e480000,0xbf7b3f80,0xbf553f6d,0xbf0e3ec4,0x3f0ebec4,0xbf553f6d,
0xbf0e3f35,0xbf553f35,0x3f55bf35,0xbf0e3f35,0xbe483ec4,0xbf7b3f6d,0x3f7bbf6d,0xbe483ec4,0x3f7fbf80,0x3dc90000,0x3f22bf35,0x3f46bf35,
0x3f75bf7b,0x3e95be48,0x3ef1bf0e,0x3f62bf55,0x3f62bf6d,0x3ef1bec4,0x3e95bec4,0x3f75bf6d,0x3f46bf55,0x3f22bf0e,0x3dc9be48,0x3f7fbf7b,
0x3f803f80,0xbf803f80,0x3f803f80,0xbf803f80,0x3f803f80,0xbf803f80,0x3f803f80,0xbf803f80,0x3f803f80,0xbf803f80,0x3f803f80,0xbf803f80,
0x3f803f80,0xbf803f80,0x3f803f80,0xbf803f80,0x3dc90000,0x3f7f3f80,0x3f463f35,0x3f223f35,0x3e953e48,0x3f753f7b,0x3f623f55,0x3ef13f0e,
0x3ef13ec4,0x3f623f6d,0x3f753f6d,0x3e953ec4,0x3f223f0e,0x3f463f55,0x3f7f3f7b,0x3dc93e48,0xbf7bbf80,0x3e480000,0x3e480000,0x3f7b3f80,
0xbf55bf6d,0x3f0e3ec4,0x3f0e3ec4,0x3f553f6d,0xbf0ebf35,0x3f553f35,0x3f553f35,0x3f0e3f35,0xbe48bec4,0x3f7b3f6d,0x3f7b3f6d,0x3e483ec4,
0xbe950000,0xbf75bf80,0xbef1bf35,0x3f623f35,0xbf46bf0e,0xbf22bf55,0x3dc9be48,0x3f7f3f7b,0xbf7fbf6d,0xbdc9bec4,0x3f223ec4,0x3f463f6d,
0xbf62bf7b,0x3ef13e48,0x3f753f55,0x3e953f0e,0x3f6d3f80,0xbec40000,0xbf6dbf80,0x3ec40000,0x3ec43f35,0xbf6dbf35,0xbec4bf35,0x3f6d3f35,
0xbec40000,0xbf6dbf80,0x3ec40000,0x3f6d3f80,0xbf6dbf35,0xbec4bf35,0x3f6d3f35,0x3ec43f35,0x3ef10000,0x3f623f80,0xbf75bf35,0xbe95bf35,
0x3f7f3f55,0x3dc93f0e,0xbf46bf7b,0x3f223e48,0x3f223f6d,0xbf46bec4,0x3dc9bec4,0x3f7f3f6d,0xbe953e48,0xbf75bf7b,0x3f623f0e,0x3ef13f55,
0xbf55bf80,0x3f0e0000,0xbf0e0000,0xbf55bf80,0x3e48bec4,0x3f7b3f6d,0xbf7bbf6d,0x3e48bec4,0x3f7b3f35,0x3e483f35,0xbe48bf35,0x3f7b3f35,
0x3f0e3f6d,0xbf55bec4,0x3f553ec4,0x3f0e3f6d,0xbf220000,0xbf46bf80,0x3dc93f35,0xbf7fbf35,0xbf62bf7b,0x3ef1be48,0xbf75bf0e,0xbe95bf55,
0x3e95bec4,0x3f753f6d,0xbef1bf6d,0x3f623ec4,0x3f7f3f55,0xbdc93f0e,0x3f463e48,0x3f223f7b,0x3f353f80,0xbf350000,0x3f353f80,0xbf350000,
0xbf350000,0xbf35bf80,0xbf350000,0xbf35bf80,0xbf35bf80,0x3f350000,0xbf35bf80,0x3f350000,0x3f350000,0x3f353f80,0x3f350000,0x3f353f80,
0x3f460000,0x3f223f80,0x3f7f3f35,0xbdc93f35,0x3ef13f7b,0xbf62be48,0xbe953f0e,0xbf75bf55,0xbf75bec4,0xbe95bf6d,0xbf62bf6d,0x3ef1bec4,
0xbdc9bf55,0x3f7f3f0e,0x3f22be48,0x3f463f7b,0xbf0ebf80,0x3f550000,0x3f550000,0x3f0e3f80,0x3f7b3ec4,0x3e483f6d,0x3e483f6d,0xbf7bbec4,
0xbe483f35,0xbf7bbf35,0xbf7bbf35,0x3e48bf35,0xbf55bf6d,0x3f0ebec4,0x3f0ebec4,0x3f553f6d,0xbf620000,0xbef1bf80,0x3e95bf35,0x3f753f35,
0x3dc9bf55,0x3f7f3f0e,0x3f223f7b,0xbf463e48,0x3f463f6d,0xbf223ec4,0xbf7fbec4,0xbdc9bf6d,0xbf75be48,0xbe95bf7b,0x3ef1bf0e,0x3f623f55,
0x3ec43f80,0xbf6d0000,0xbec4bf80,0x3f6d0000,0xbf6dbf35,0x3ec4bf35,0x3f6d3f35,0xbec43f35,0x3f6d0000,0x3ec43f80,0xbf6d0000,0xbec4bf80,
0xbec43f35,0xbf6dbf35,0x3ec4bf35,0x3f6d3f35,0x3f750000,0x3e953f80,0xbf62bf35,0x3ef1bf35,0xbf223f0e,0xbf46bf55,0x3f7f3e48,0x3dc93f7b,
0x3dc9bf6d,0x3f7f3ec4,0xbf463ec4,0xbf22bf6d,0x3ef13f7b,0xbf623e48,0x3e95bf55,0x3f753f0e,0xbe48bf80,0x3f7b0000,0xbf7b0000,0xbe48bf80,
0x3f0e3f6d,0xbf553ec4,0x3f55bec4,0x3f0e3f6d,0xbf55bf35,0x3f0ebf35,0xbf0e3f35,0xbf55bf35,0x3f7b3ec4,0xbe483f6d,0x3e48bf6d,0x3f7b3ec4,
0xbf7f0000,0xbdc9bf80,0xbf223f35,0xbf46bf35,0x3f75be48,0x3e953f7b,0x3ef1bf55,0x3f623f0e,0xbf623ec4,0xbef1bf6d,0xbe953f6d,0xbf75bec4,
0x3f46bf0e,0x3f223f55,0x3dc9bf7b,0x3f7f3e48,0x3f80,0xbf800000,0x3f80,0xbf800000,0xbf80,0x3f800000,0xbf80,0x3f800000,
0x3f80,0xbf800000,0x3f80,0xbf800000,0xbf80,0x3f800000,0xbf80,0x3f800000,0x3f7f0000,0xbdc93f80,0x3f223f35,0xbf463f35,
0xbf75be48,0x3e95bf7b,0xbef1bf55,0x3f62bf0e,0x3f623ec4,0xbef13f6d,0x3e953f6d,0xbf753ec4,0xbf46bf0e,0x3f22bf55,0xbdc9bf7b,0x3f7fbe48,
0x3e48bf80,0x3f7b0000,0x3f7b0000,0xbe483f80,0xbf0e3f6d,0xbf55bec4,0xbf55bec4,0x3f0ebf6d,0x3f55bf35,0x3f0e3f35,0x3f0e3f35,0xbf553f35,
0xbf7b3ec4,0xbe48bf6d,0xbe48bf6d,0x3f7bbec4,0xbf750000,0x3e95bf80,0x3f62bf35,0x3ef13f35,0x3f223f0e,0xbf463f55,0xbf7f3e48,0x3dc9bf7b,
0xbdc9bf6d,0x3f7fbec4,0x3f463ec4,0xbf223f6d,0xbef13f7b,0xbf62be48,0xbe95bf55,0x3f75bf0e,0xbec43f80,0xbf6d0000,0x3ec4bf80,0x3f6d0000,
0x3f6dbf35,0x3ec43f35,0xbf6d3f35,0xbec4bf35,0xbf6d0000,0x3ec4bf80,0x3f6d0000,0xbec43f80,0x3ec43f35,0xbf6d3f35,0xbec4bf35,0x3f6dbf35,
0x3f620000,0xbef13f80,0xbe95bf35,0x3f75bf35,0xbdc9bf55,0x3f7fbf0e,0xbf223f7b,0xbf46be48,0xbf463f6d,0xbf22bec4,0x3f7fbec4,0xbdc93f6d,
0x3f75be48,0xbe953f7b,0xbef1bf0e,0x3f62bf55,0x3f0ebf80,0x3f550000,0xbf550000,0x3f0ebf80,0xbf7b3ec4,0x3e48bf6d,0xbe483f6d,0xbf7b3ec4,
0x3e483f35,0xbf7b3f35,0x3f7bbf35,0x3e483f35,0x3f55bf6d,0x3f0e3ec4,0xbf0ebec4,0x3f55bf6d,0xbf460000,0x3f22bf80,0xbf7f3f35,0xbdc9bf35,
0xbef13f7b,0xbf623e48,0x3e953f0e,0xbf753f55,0x3f75bec4,0xbe953f6d,0x3f62bf6d,0x3ef13ec4,0x3dc9bf55,0x3f7fbf0e,0xbf22be48,0x3f46bf7b,
0xbf353f80,0xbf350000,0xbf353f80,0xbf350000,0x3f350000,0xbf353f80,0x3f350000,0xbf353f80,0x3f35bf80,0x3f350000,0x3f35bf80,0x3f350000,
0xbf350000,0x3f35bf80,0xbf350000,0x3f35bf80,0x3f220000,0xbf463f80,0xbdc93f35,0xbf7f3f35,0x3f62bf7b,0x3ef13e48,0x3f75bf0e,0xbe953f55,
0xbe95bec4,0x3f75bf6d,0x3ef1bf6d,0x3f62bec4,0xbf7f3f55,0xbdc9bf0e,0xbf463e48,0x3f22bf7b,0x3f55bf80,0x3f0e0000,0x3f0e0000,0xbf553f80,
0xbe48bec4,0x3f7bbf6d,0x3f7bbf6d,0x3e483ec4,0xbf7b3f35,0x3e48bf35,0x3e48bf35,0x3f7bbf35,0xbf0e3f6d,0xbf553ec4,0xbf553ec4,0x3f0ebf6d,
0xbef10000,0x3f62bf80,0x3f75bf35,0xbe953f35,0xbf7f3f55,0x3dc9bf0e,0x3f46bf7b,0x3f22be48,0xbf223f6d,0xbf463ec4,0xbdc9bec4,0x3f7fbf6d,
0x3e953e48,0xbf753f7b,0xbf623f0e,0x3ef1bf55,0xbf6d3f80,0xbec40000,0x3f6dbf80,0x3ec40000,0xbec43f35,0xbf6d3f35,0x3ec4bf35,0x3f6dbf35,
0x3ec40000,0xbf6d3f80,0xbec40000,0x3f6dbf80,0x3f6dbf35,0xbec43f35,0xbf6d3f35,0x3ec4bf35,0x3e950000,0xbf753f80,0x3ef1bf35,0x3f62bf35,
0x3f46bf0e,0xbf223f55,0xbdc9be48,0x3f7fbf7b,0x3f7fbf6d,0xbdc93ec4,0xbf223ec4,0x3f46bf6d,0x3f62bf7b,0x3ef1be48,0xbf753f55,0x3e95bf0e,
0x3f7bbf80,0x3e480000,0xbe480000,0x3f7bbf80,0x3f55bf6d,0x3f0ebec4,0xbf0e3ec4,0x3f55bf6d,0x3f0ebf35,0x3f55bf35,0xbf553f35,0x3f0ebf35,
0x3e48bec4,0x3f7bbf6d,0xbf7b3f6d,0x3e48bec4,0xbdc90000,0x3f7fbf80,0xbf463f35,0x3f22bf35,0xbe953e48,0x3f75bf7b,0xbf623f55,0x3ef1bf0e,
0xbef13ec4,0x3f62bf6d,0xbf753f6d,0x3e95bec4,0xbf223f0e,0x3f46bf55,0xbf7f3f7b,0x3dc9be48,0x40003f80,0x3fb53f80,0x3f80,0xbfb53f80,
0x40004000,0xbfb50000,0x0,0xbfb5c000,0x40004000,0xbfb5c000,0x0,0x3fb50000,0x40004000,0x3fb50000,0x0,0x3fb54000,
0x3fff3f80,0x3fa23f80,0xbe49bf80,0xbfc6bf80,0x3ff53ffb,0xbfe2bec8,0xbf15bec8,0xbf71bffb,0x3fe23fed,0xbf15bfed,0xbf71bf44,0x3ff53f44,
0x3fc63fd5,0x3fff3f8e,0xbfa2bf8e,0x3e493fd5,0x3ffb3f80,0x3f8e3f80,0xbec83f80,0xbfd53f80,0x3fd53fed,0xbffbbf44,0xbf8ebf44,0xbec8bfed,
0x3f8e3fb5,0x3ec8bfb5,0xbfd5bfb5,0x3ffb3fb5,0x3ec83f44,0x3fd53fed,0xbffbbfed,0xbf8e3f44,0x3ff53f80,0x3f713f80,0xbf15bf80,0xbfe2bf80,
0x3fa23fd5,0xbfffbf8e,0xbfc6bf8e,0x3e49bfd5,0x3e493f44,0x3fa2bf44,0xbfffbfed,0x3fc63fed,0xbf71bec8,0x3f153ffb,0xbfe2bffb,0xbff5bec8,
0x3fed3f80,0x3f443f80,0xbf443f80,0xbfed3f80,0x3f443fb5,0xbfedbfb5,0xbfedbfb5,0x3f44bfb5,0xbf440000,0x3fed0000,0xbfedc000,0x3f444000,
0xbfedbfb5,0xbf443fb5,0xbf44bfb5,0xbfedbfb5,0x3fe23f80,0x3f153f80,0xbf71bf80,0xbff5bf80,0x3e493f8e,0xbfc6bfd5,0xbfffbfd5,0x3fa2bf8e,
0xbfc6bf44,0x3fff3f44,0xbfa2bfed,0xbe493fed,0xbff5bffb,0xbfe23ec8,0x3f15bec8,0xbf71bffb,0x3fd53f80,0x3ec83f80,0xbf8e3f80,0xbffb3f80,
0xbec83f44,0xbf8ebfed,0xbffbbfed,0x3fd5bf44,0xbffbbfb5,0x3fd53fb5,0xbec8bfb5,0xbf8e3fb5,0xbf8ebfed,0xbffbbf44,0x3fd53f44,0x3ec8bfed,
0x3fc63f80,0x3e493f80,0xbfa2bf80,0xbfffbf80,0xbf713ec8,0xbf15bffb,0xbfe2bffb,0x3ff5bec8,0xbff5bfed,0x3f713fed,0x3f15bf44,0xbfe23f44,
0x3e49bf8e,0xbfa2bfd5,0x3fff3fd5,0x3fc6bf8e,0x3f80,0xbfb53f80,0xc0003f80,0xbfb53f80,0xc000,0x3fb50000,0x40000000,0xbfb54000,
0x4000,0x3fb5c000,0xc0000000,0x3fb50000,0xc000,0xbfb50000,0x40000000,0x3fb5c000,0xbe493f80,0xbfc63f80,0xbfffbf80,0xbfa2bf80,
0x3f15bffb,0x3f713ec8,0x3ff53ec8,0xbfe23ffb,0xbf713fed,0x3ff5bfed,0xbfe2bf44,0x3f153f44,0x3fa2bfd5,0xbe49bf8e,0x3fc63f8e,0x3fffbfd5,
0xbec83f80,0xbfd53f80,0xbffb3f80,0xbf8e3f80,0x3f8ebfed,0x3ec83f44,0x3fd53f44,0xbffb3fed,0xbfd53fb5,0x3ffbbfb5,0xbf8ebfb5,0xbec83fb5,
0x3ffbbf44,0x3f8ebfed,0x3ec83fed,0x3fd5bf44,0xbf153f80,0xbfe23f80,0xbff5bf80,0xbf71bf80,0x3fc6bfd5,0xbe493f8e,0x3fa23f8e,0xbfff3fd5,
0xbfff3f44,0x3fc6bf44,0xbe49bfed,0xbfa23fed,0x3fe23ec8,0x3ff5bffb,0xbf713ffb,0x3f153ec8,0xbf443f80,0xbfed3f80,0xbfed3f80,0xbf443f80,
0x3fedbfb5,0xbf443fb5,0x3f443fb5,0xbfed3fb5,0xbfed0000,0x3f440000,0x3f44c000,0xbfed4000,0x3f443fb5,0x3fedbfb5,0xbfed3fb5,0xbf443fb5,
0xbf713f80,0xbff53f80,0xbfe2bf80,0xbf15bf80,0x3fffbf8e,0xbfa23fd5,0x3e493fd5,0xbfc63f8e,0xbfa2bf44,0xbe493f44,0x3fc6bfed,0xbfff3fed,
0xbf153ffb,0x3f71bec8,0xbff53ec8,0xbfe23ffb,0xbf8e3f80,0xbffb3f80,0xbfd53f80,0xbec83f80,0x3ffbbf44,0xbfd53fed,0xbec83fed,0xbf8e3f44,
0xbec8bfb5,0xbf8e3fb5,0x3ffbbfb5,0xbfd53fb5,0xbfd53fed,0xbec83f44,0xbf8ebf44,0xbffb3fed,0xbfa23f80,0xbfff3f80,0xbfc6bf80,0xbe49bf80,
0x3fe2bec8,0xbff53ffb,0xbf713ffb,0xbf153ec8,0x3f15bfed,0xbfe23fed,0x3ff5bf44,0xbf713f44,0xbfff3f8e,0xbfc63fd5,0x3e49bfd5,0xbfa23f8e,
0xc0003f80,0xbfb53f80,0x3f80,0x3fb53f80,0xc0004000,0x3fb50000,0x0,0x3fb5c000,0xc0004000,0x3fb5c000,0x0,0xbfb50000,
0xc0004000,0xbfb50000,0x0,0xbfb54000,0xbfff3f80,0xbfa23f80,0x3e49bf80,0x3fc6bf80,0xbff53ffb,0x3fe2bec8,0x3f15bec8,0x3f71bffb,
0xbfe23fed,0x3f15bfed,0x3f71bf44,0xbff53f44,0xbfc63fd5,0xbfff3f8e,0x3fa2bf8e,0xbe493fd5,0xbffb3f80,0xbf8e3f80,0x3ec83f80,0x3fd53f80,
0xbfd53fed,0x3ffbbf44,0x3f8ebf44,0x3ec8bfed,0xbf8e3fb5,0xbec8bfb5,0x3fd5bfb5,0xbffb3fb5,0xbec83f44,0xbfd53fed,0x3ffbbfed,0x3f8e3f44,
0xbff53f80,0xbf713f80,0x3f15bf80,0x3fe2bf80,0xbfa23fd5,0x3fffbf8e,0x3fc6bf8e,0xbe49bfd5,0xbe493f44,0xbfa2bf44,0x3fffbfed,0xbfc63fed,
0x3f71bec8,0xbf153ffb,0x3fe2bffb,0x3ff5bec8,0xbfed3f80,0xbf443f80,0x3f443f80,0x3fed3f80,0xbf443fb5,0x3fedbfb5,0x3fedbfb5,0xbf44bfb5,
0x3f440000,0xbfed0000,0x3fedc000,0xbf444000,0x3fedbfb5,0x3f443fb5,0x3f44bfb5,0x3fedbfb5,0xbfe23f80,0xbf153f80,0x3f71bf80,0x3ff5bf80,
0xbe493f8e,0x3fc6bfd5,0x3fffbfd5,0xbfa2bf8e,0x3fc6bf44,0xbfff3f44,0x3fa2bfed,0x3e493fed,0x3ff5bffb,0x3fe23ec8,0xbf15bec8,0x3f71bffb,
0xbfd53f80,0xbec83f80,0x3f8e3f80,0x3ffb3f80,0x3ec83f44,0x3f8ebfed,0x3ffbbfed,0xbfd5bf44,0x3ffbbfb5,0xbfd53fb5,0x3ec8bfb5,0x3f8e3fb5,
0x3f8ebfed,0x3ffbbf44,0xbfd53f44,0xbec8bfed,0xbfc63f80,0xbe493f80,0x3fa2bf80,0x3fffbf80,0x3f713ec8,0x3f15bffb,0x3fe2bffb,0xbff5bec8,
0x3ff5bfed,0xbf713fed,0xbf15bf44,0x3fe23f44,0xbe49bf8e,0x3fa2bfd5,0xbfff3fd5,0xbfc6bf8e,0x3f80,0x3fb53f80,0x40003f80,0x3fb53f80,
0xc000,0xbfb50000,0xc0000000,0x3fb54000,0x4000,0xbfb5c000,0x40000000,0xbfb50000,0xc000,0x3fb50000,0xc0000000,0xbfb5c000,
0x3e493f80,0x3fc63f80,0x3fffbf80,0x3fa2bf80,0xbf15bffb,0xbf713ec8,0xbff53ec8,0x3fe23ffb,0x3f713fed,0xbff5bfed,0x3fe2bf44,0xbf153f44,
0xbfa2bfd5,0x3e49bf8e,0xbfc63f8e,0xbfffbfd5,0x3ec83f80,0x3fd53f80,0x3ffb3f80,0x3f8e3f80,0xbf8ebfed,0xbec83f44,0xbfd53f44,0x3ffb3fed,
0x3fd53fb5,0xbffbbfb5,0x3f8ebfb5,0x3ec83fb5,0xbffbbf44,0xbf8ebfed,0xbec83fed,0xbfd5bf44,0x3f153f80,0x3fe23f80,0x3ff5bf80,0x3f71bf80,
0xbfc6bfd5,0x3e493f8e,0xbfa23f8e,0x3fff3fd5,0x3fff3f44,0xbfc6bf44,0x3e49bfed,0x3fa23fed,0xbfe23ec8,0xbff5bffb,0x3f713ffb,0xbf153ec8,
0x3f443f80,0x3fed3f80,0x3fed3f80,0x3f443f80,0xbfedbfb5,0x3f443fb5,0xbf443fb5,0x3fed3fb5,0x3fed0000,0xbf440000,0xbf44c000,0x3fed4000,
0xbf443fb5,0xbfedbfb5,0x3fed3fb5,0x3f443fb5,0x3f713f80,0x3ff53f80,0x3fe2bf80,0x3f15bf80,0xbfffbf8e,0x3fa23fd5,0xbe493fd5,0x3fc63f8e,
0x3fa2bf44,0x3e493f44,0xbfc6bfed,0x3fff3fed,0x3f153ffb,0xbf71bec8,0x3ff53ec8,0x3fe23ffb,0x3f8e3f80,0x3ffb3f80,0x3fd53f80,0x3ec83f80,
0xbffbbf44,0x3fd53fed,0x3ec83fed,0x3f8e3f44,0x3ec8bfb5,0x3f8e3fb5,0xbffbbfb5,0x3fd53fb5,0x3fd53fed,0x3ec83f44,0x3f8ebf44,0x3ffb3fed,
0x3fa23f80,0x3fff3f80,0x3fc6bf80,0x3e49bf80,0xbfe2bec8,0x3ff53ffb,0x3f713ffb,0x3f153ec8,0xbf15bfed,0x3fe23fed,0xbff5bf44,0x3f713f44,
0x3fff3f8e,0x3fc63fd5,0xbe49bfd5,0x3fa23f8e,0x40004000,0x3fb54000,0x0,0xbfb50000,0x40004000,0xbfb50000,0x0,0xbfb5c000,
0x40004000,0xbfb5c000,0x0,0x3fb50000,0x40004000,0x3fb50000,0x0,0x3fb54000,0x3fa23fb5,0xbe493fb5,0xbfc6bfb5,0xbfffbfb5,
0x3f713f8e,0xbff5bfd5,0xbfe2bfd5,0x3f15bf8e,0x3f153f44,0x3f71bf44,0xbff5bfed,0x3fe23fed,0x3e493ec8,0x3fc63ffb,0xbfffbffb,0xbfa23ec8,
0xbec80000,0xbfd50000,0xbffbc000,0xbf8ec000,0xbf8ebf44,0xbec8bfed,0xbfd5bfed,0x3ffb3f44,0xbfd5bfb5,0x3ffb3fb5,0xbf8ebfb5,0xbec83fb5,
0xbffbbfed,0xbf8e3f44,0xbec8bf44,0xbfd5bfed,0xbfe2bfb5,0xbff5bfb5,0xbf71bfb5,0x3f15bfb5,0xbfffbffb,0x3fc6bec8,0x3e49bec8,0x3fa23ffb,
0xbfc6bfed,0x3e493fed,0x3fa23f44,0xbfffbf44,0xbf15bf8e,0xbfe2bfd5,0x3ff53fd5,0x3f71bf8e,0xbfedc000,0xbf44c000,0x3f440000,0x3fed0000,
0xbf44bfb5,0x3fed3fb5,0x3fed3fb5,0xbf443fb5,0x3f440000,0xbfed0000,0x3fed4000,0xbf44c000,0x3fed3fb5,0x3f44bfb5,0x3f443fb5,0x3fed3fb5,
0xbf15bfb5,0x3f71bfb5,0x3ff53fb5,0x3fe23fb5,0x3fa23ec8,0x3e493ffb,0x3fc63ffb,0xbfffbec8,0x3fff3fed,0xbfa2bfed,0xbe493f44,0x3fc6bf44,
0x3f713fd5,0x3ff53f8e,0xbfe2bf8e,0xbf153fd5,0x3f8e0000,0x3ffb0000,0x3fd54000,0x3ec84000,0x3ffb3fed,0xbfd53f44,0xbec83f44,0xbf8ebfed,
0x3ec83fb5,0x3f8ebfb5,0xbffbbfb5,0x3fd53fb5,0xbfd5bf44,0xbec83fed,0xbf8ebfed,0xbffbbf44,0x3fff3fb5,0x3fc63fb5,0x3e493fb5,0xbfa23fb5,
0x3f153fd5,0xbfe2bf8e,0xbff5bf8e,0x3f71bfd5,0xbfe2bf44,0x3ff53f44,0xbf71bfed,0xbf153fed,0xbfa2bffb,0xbfffbec8,0x3fc63ec8,0x3e49bffb,
0x4000,0xbfb54000,0xc0000000,0xbfb50000,0xc000,0x3fb50000,0x40000000,0xbfb54000,0x4000,0x3fb5c000,0xc0000000,0x3fb50000,
0xc000,0xbfb50000,0x40000000,0x3fb5c000,0xbfc63fb5,0xbfff3fb5,0xbfa2bfb5,0x3e49bfb5,0x3fe2bf8e,0xbf153fd5,0x3f713fd5,0xbff53f8e,
0xbff53f44,0x3fe2bf44,0xbf15bfed,0xbf713fed,0x3fffbec8,0x3fa2bffb,0x3e493ffb,0x3fc6bec8,0xbffb0000,0xbf8e0000,0x3ec8c000,0x3fd5c000,
0x3fd53f44,0xbffb3fed,0xbf8e3fed,0xbec8bf44,0xbf8ebfb5,0xbec83fb5,0x3fd5bfb5,0xbffb3fb5,0x3ec83fed,0x3fd5bf44,0xbffb3f44,0xbf8e3fed,
0xbf71bfb5,0x3f15bfb5,0x3fe2bfb5,0x3ff5bfb5,0xbe493ffb,0xbfa23ec8,0xbfff3ec8,0x3fc6bffb,0x3fa2bfed,0xbfff3fed,0x3fc63f44,0xbe49bf44,
0xbff53f8e,0xbf713fd5,0xbf15bfd5,0xbfe23f8e,0x3f44c000,0x3fedc000,0x3fed0000,0x3f440000,0xbfed3fb5,0x3f44bfb5,0xbf44bfb5,0x3fedbfb5,
0x3fed0000,0xbf440000,0xbf444000,0x3fedc000,0xbf44bfb5,0xbfed3fb5,0x3fedbfb5,0x3f44bfb5,0x3ff5bfb5,0x3fe2bfb5,0x3f153fb5,0xbf713fb5,
0xbfc6bec8,0x3fffbffb,0x3fa2bffb,0x3e493ec8,0xbe493fed,0x3fc6bfed,0xbfff3f44,0x3fa2bf44,0x3fe2bfd5,0x3f15bf8e,0x3f713f8e,0x3ff5bfd5,
0x3fd50000,0x3ec80000,0xbf8e4000,0xbffb4000,0x3ec8bfed,0x3f8ebf44,0x3ffbbf44,0xbfd53fed,0xbffb3fb5,0x3fd5bfb5,0xbec8bfb5,0xbf8e3fb5,
0x3f8e3f44,0x3ffbbfed,0xbfd53fed,0xbec83f44,0x3e493fb5,0xbfa23fb5,0xbfff3fb5,0xbfc63fb5,0x3ff5bfd5,0xbf713f8e,0x3f153f8e,0xbfe23fd5,
0xbf71bf44,0xbf153f44,0x3fe2bfed,0xbff53fed,0xbfc63ffb,0xbe493ec8,0xbfa2bec8,0xbfff3ffb,0xc0004000,0xbfb54000,0x0,0x3fb50000,
0xc0004000,0x3fb50000,0x0,0x3fb5c000,0xc0004000,0x3fb5c000,0x0,0xbfb50000,0xc0004000,0xbfb50000,0x0,0xbfb54000,
0xbfa23fb5,0x3e493fb5,0x3fc6bfb5,0x3fffbfb5,0xbf713f8e,0x3ff5bfd5,0x3fe2bfd5,0xbf15bf8e,0xbf153f44,0xbf71bf44,0x3ff5bfed,0xbfe23fed,
0xbe493ec8,0xbfc63ffb,0x3fffbffb,0x3fa23ec8,0x3ec80000,0x3fd50000,0x3ffbc000,0x3f8ec000,0x3f8ebf44,0x3ec8bfed,0x3fd5bfed,0xbffb3f44,
0x3fd5bfb5,0xbffb3fb5,0x3f8ebfb5,0x3ec83fb5,0x3ffbbfed,0x3f8e3f44,0x3ec8bf44,0x3fd5bfed,0x3fe2bfb5,0x3ff5bfb5,0x3f71bfb5,0xbf15bfb5,
0x3fffbffb,0xbfc6bec8,0xbe49bec8,0xbfa23ffb,0x3fc6bfed,0xbe493fed,0xbfa23f44,0x3fffbf44,0x3f15bf8e,0x3fe2bfd5,0xbff53fd5,0xbf71bf8e,
0x3fedc000,0x3f44c000,0xbf440000,0xbfed0000,0x3f44bfb5,0xbfed3fb5,0xbfed3fb5,0x3f443fb5,0xbf440000,0x3fed0000,0xbfed4000,0x3f44c000,
0xbfed3fb5,0xbf44bfb5,0xbf443fb5,0xbfed3fb5,0x3f15bfb5,0xbf71bfb5,0xbff53fb5,0xbfe23fb5,0xbfa23ec8,0xbe493ffb,0xbfc63ffb,0x3fffbec8,
0xbfff3fed,0x3fa2bfed,0x3e493f44,0xbfc6bf44,0xbf713fd5,0xbff53f8e,0x3fe2bf8e,0x3f153fd5,0xbf8e0000,0xbffb0000,0xbfd54000,0xbec84000,
0xbffb3fed,0x3fd53f44,0x3ec83f44,0x3f8ebfed,0xbec83fb5,0xbf8ebfb5,0x3ffbbfb5,0xbfd53fb5,0x3fd5bf44,0x3ec83fed,0x3f8ebfed,0x3ffbbf44,
0xbfff3fb5,0xbfc63fb5,0xbe493fb5,0x3fa23fb5,0xbf153fd5,0x3fe2bf8e,0x3ff5bf8e,0xbf71bfd5,0x3fe2bf44,0xbff53f44,0x3f71bfed,0x3f153fed,
0x3fa2bffb,0x3fffbec8,0xbfc63ec8,0xbe49bffb,0x4000,0x3fb54000,0x40000000,0x3fb50000,0xc000,0xbfb50000,0xc0000000,0x3fb54000,
0x4000,0xbfb5c000,0x40000000,0xbfb50000,0xc000,0x3fb50000,0xc0000000,0xbfb5c000,0x3fc63fb5,0x3fff3fb5,0x3fa2bfb5,0xbe49bfb5,
0xbfe2bf8e,0x3f153fd5,0xbf713fd5,0x3ff53f8e,0x3ff53f44,0xbfe2bf44,0x3f15bfed,0x3f713fed,0xbfffbec8,0xbfa2bffb,0xbe493ffb,0xbfc6bec8,
0x3ffb0000,0x3f8e0000,0xbec8c000,0xbfd5c000,0xbfd53f44,0x3ffb3fed,0x3f8e3fed,0x3ec8bf44,0x3f8ebfb5,0x3ec83fb5,0xbfd5bfb5,0x3ffb3fb5,
0xbec83fed,0xbfd5bf44,0x3ffb3f44,0x3f8e3fed,0x3f71bfb5,0xbf15bfb5,0xbfe2bfb5,0xbff5bfb5,0x3e493ffb,0x3fa23ec8,0x3fff3ec8,0xbfc6bffb,
0xbfa2bfed,0x3fff3fed,0xbfc63f44,0x3e49bf44,0x3ff53f8e,0x3f713fd5,0x3f15bfd5,0x3fe23f8e,0xbf44c000,0xbfedc000,0xbfed0000,0xbf440000,
0x3fed3fb5,0xbf44bfb5,0x3f44bfb5,0xbfedbfb5,0xbfed0000,0x3f440000,0x3f444000,0xbfedc000,0x3f44bfb5,0x3fed3fb5,0xbfedbfb5,0xbf44bfb5,
0xbff5bfb5,0xbfe2bfb5,0xbf153fb5,0x3f713fb5,0x3fc6bec8,0xbfffbffb,0xbfa2bffb,0xbe493ec8,0x3e493fed,0xbfc6bfed,0x3fff3f44,0xbfa2bf44,
0xbfe2bfd5,0xbf15bf8e,0xbf713f8e,0xbff5bfd5,0xbfd50000,0xbec80000,0x3f8e4000,0x3ffb4000,0xbec8bfed,0xbf8ebf44,0xbffbbf44,0x3fd53fed,
0x3ffb3fb5,0xbfd5bfb5,0x3ec8bfb5,0x3f8e3fb5,0xbf8e3f44,0xbffbbfed,0x3fd53fed,0x3ec83f44,0xbe493fb5,0x3fa23fb5,0x3fff3fb5,0x3fc63fb5,
0xbff5bfd5,0x3f713f8e,0xbf153f8e,0x3fe23fd5,0x3f71bf44,0x3f153f44,0xbfe2bfed,0x3ff53fed,0x3fc63ffb,0x3e493ec8,0x3fa2bec8,0x3fff3ffb,
0x40004000,0x3fb54000,0x0,0xbfb50000,0x40004000,0xbfb50000,0x0,0xbfb5c000,0x40004000,0xbfb5c000,0x0,0x3fb50000,
0x40004000,0x3fb50000,0x0,0x3fb54000,0xbe490000,0xbfc60000,0xbfffc000,0xbfa2c000,0xbf15bec8,0xbf71bffb,0xbff5bffb,0x3fe23ec8,
0xbf71bf44,0x3ff53f44,0xbfe2bfed,0x3f153fed,0xbfa2bf8e,0x3e493fd5,0xbfc6bfd5,0xbfffbf8e,0xbffbc000,0xbf8ec000,0x3ec80000,0x3fd50000,
0xbfd5bfed,0x3ffb3f44,0x3f8e3f44,0x3ec83fed,0xbf8ebfb5,0xbec83fb5,0x3fd53fb5,0xbffbbfb5,0xbec8bf44,0xbfd5bfed,0x3ffb3fed,0x3f8ebf44,
0x3f150000,0x3fe20000,0x3ff54000,0x3f714000,0x3fc63f8e,0xbe493fd5,0x3fa23fd5,0xbfffbf8e,0x3fff3fed,0xbfc6bfed,0x3e493f44,0x3fa2bf44,
0x3fe23ffb,0x3ff53ec8,0xbf71bec8,0x3f153ffb,0x3fed4000,0x3f444000,0xbf440000,0xbfed0000,0x3f443fb5,0xbfedbfb5,0xbfedbfb5,0x3f44bfb5,
0xbf440000,0x3fed0000,0xbfedc000,0x3f444000,0xbfedbfb5,0xbf443fb5,0xbf44bfb5,0xbfedbfb5,0xbf710000,0xbff50000,0xbfe2c000,0xbf15c000,
0xbfffbfd5,0x3fa2bf8e,0xbe49bf8e,0x3fc63fd5,0xbfa2bfed,0xbe493fed,0x3fc63f44,0xbfffbf44,0x3f15bec8,0xbf71bffb,0x3ff53ffb,0x3fe2bec8,
0xbfd5c000,0xbec8c000,0x3f8e0000,0x3ffb0000,0x3ec8bf44,0x3f8e3fed,0x3ffb3fed,0xbfd53f44,0x3ffb3fb5,0xbfd5bfb5,0x3ec83fb5,0x3f8ebfb5,
0x3f8e3fed,0x3ffb3f44,0xbfd5bf44,0xbec83fed,0x3fa20000,0x3fff0000,0x3fc64000,0x3e494000,0x3fe23ffb,0xbff53ec8,0xbf713ec8,0xbf15bffb,
0xbf153f44,0x3fe2bf44,0xbff5bfed,0x3f713fed,0xbfffbfd5,0xbfc63f8e,0x3e49bf8e,0xbfa2bfd5,0x4000,0xbfb54000,0xc0000000,0xbfb50000,
0xc000,0x3fb50000,0x40000000,0xbfb54000,0x4000,0x3fb5c000,0xc0000000,0x3fb50000,0xc000,0xbfb50000,0x40000000,0x3fb5c000,
0xbfff0000,0xbfa20000,0x3e49c000,0x3fc6c000,0x3ff53ec8,0xbfe23ffb,0xbf153ffb,0xbf71bec8,0xbfe2bf44,0x3f153f44,0x3f71bfed,0xbff53fed,
0x3fc63f8e,0x3fffbfd5,0xbfa23fd5,0x3e493f8e,0x3ec8c000,0x3fd5c000,0x3ffb0000,0x3f8e0000,0xbf8e3fed,0xbec8bf44,0xbfd5bf44,0x3ffbbfed,
0x3fd5bfb5,0xbffb3fb5,0x3f8e3fb5,0x3ec8bfb5,0xbffb3f44,0xbf8e3fed,0xbec8bfed,0xbfd53f44,0x3ff50000,0x3f710000,0xbf154000,0xbfe24000,
0xbfa2bf8e,0x3fffbfd5,0x3fc6bfd5,0xbe493f8e,0x3e493fed,0x3fa2bfed,0xbfff3f44,0x3fc6bf44,0x3f71bffb,0xbf15bec8,0x3fe23ec8,0x3ff5bffb,
0xbf444000,0xbfed4000,0xbfed0000,0xbf440000,0x3fedbfb5,0xbf443fb5,0x3f443fb5,0xbfed3fb5,0xbfed0000,0x3f440000,0x3f44c000,0xbfed4000,
0x3f443fb5,0x3fedbfb5,0xbfed3fb5,0xbf443fb5,0xbfe20000,0xbf150000,0x3f71c000,0x3ff5c000,0x3e493fd5,0xbfc63f8e,0xbfff3f8e,0x3fa2bfd5,
0x3fc6bfed,0xbfff3fed,0x3fa23f44,0x3e49bf44,0xbff53ec8,0xbfe23ffb,0x3f15bffb,0xbf713ec8,0x3f8ec000,0x3ffbc000,0x3fd50000,0x3ec80000,
0xbffb3f44,0x3fd5bfed,0x3ec8bfed,0x3f8ebf44,0x3ec83fb5,0x3f8ebfb5,0xbffb3fb5,0x3fd5bfb5,0x3fd5bfed,0x3ec8bf44,0x3f8e3f44,0x3ffbbfed,
0x3fc60000,0x3e490000,0xbfa24000,0xbfff4000,0x3f71bffb,0x3f15bec8,0x3fe2bec8,0xbff53ffb,0xbff53f44,0x3f71bf44,0x3f15bfed,0xbfe23fed,
0xbe493fd5,0x3fa2bf8e,0xbfff3f8e,0xbfc63fd5,0xc0004000,0xbfb54000,0x0,0x3fb50000,0xc0004000,0x3fb50000,0x0,0x3fb5c000,
0xc0004000,0x3fb5c000,0x0,0xbfb50000,0xc0004000,0xbfb50000,0x0,0xbfb54000,0x3e490000,0x3fc60000,0x3fffc000,0x3fa2c000,
0x3f15bec8,0x3f71bffb,0x3ff5bffb,0xbfe23ec8,0x3f71bf44,0xbff53f44,0x3fe2bfed,0xbf153fed,0x3fa2bf8e,0xbe493fd5,0x3fc6bfd5,0x3fffbf8e,
0x3ffbc000,0x3f8ec000,0xbec80000,0xbfd50000,0x3fd5bfed,0xbffb3f44,0xbf8e3f44,0xbec83fed,0x3f8ebfb5,0x3ec83fb5,0xbfd53fb5,0x3ffbbfb5,
0x3ec8bf44,0x3fd5bfed,0xbffb3fed,0xbf8ebf44,0xbf150000,0xbfe20000,0xbff54000,0xbf714000,0xbfc63f8e,0x3e493fd5,0xbfa23fd5,0x3fffbf8e,
0xbfff3fed,0x3fc6bfed,0xbe493f44,0xbfa2bf44,0xbfe23ffb,0xbff53ec8,0x3f71bec8,0xbf153ffb,0xbfed4000,0xbf444000,0x3f440000,0x3fed0000,
0xbf443fb5,0x3fedbfb5,0x3fedbfb5,0xbf44bfb5,0x3f440000,0xbfed0000,0x3fedc000,0xbf444000,0x3fedbfb5,0x3f443fb5,0x3f44bfb5,0x3fedbfb5,
0x3f710000,0x3ff50000,0x3fe2c000,0x3f15c000,0x3fffbfd5,0xbfa2bf8e,0x3e49bf8e,0xbfc63fd5,0x3fa2bfed,0x3e493fed,0xbfc63f44,0x3fffbf44,
0xbf15bec8,0x3f71bffb,0xbff53ffb,0xbfe2bec8,0x3fd5c000,0x3ec8c000,0xbf8e0000,0xbffb0000,0xbec8bf44,0xbf8e3fed,0xbffb3fed,0x3fd53f44,
0xbffb3fb5,0x3fd5bfb5,0xbec83fb5,0xbf8ebfb5,0xbf8e3fed,0xbffb3f44,0x3fd5bf44,0x3ec83fed,0xbfa20000,0xbfff0000,0xbfc64000,0xbe494000,
0xbfe23ffb,0x3ff53ec8,0x3f713ec8,0x3f15bffb,0x3f153f44,0xbfe2bf44,0x3ff5bfed,0xbf713fed,0x3fffbfd5,0x3fc63f8e,0xbe49bf8e,0x3fa2bfd5,
0x4000,0x3fb54000,0x40000000,0x3fb50000,0xc000,0xbfb50000,0xc0000000,0x3fb54000,0x4000,0xbfb5c000,0x40000000,0xbfb50000,
0xc000,0x3fb50000,0xc0000000,0xbfb5c000,0x3fff0000,0x3fa20000,0xbe49c000,0xbfc6c000,0xbff53ec8,0x3fe23ffb,0x3f153ffb,0x3f71bec8,
0x3fe2bf44,0xbf153f44,0xbf71bfed,0x3ff53fed,0xbfc63f8e,0xbfffbfd5,0x3fa23fd5,0xbe493f8e,0xbec8c000,0xbfd5c000,0xbffb0000,0xbf8e0000,
0x3f8e3fed,0x3ec8bf44,0x3fd5bf44,0xbffbbfed,0xbfd5bfb5,0x3ffb3fb5,0xbf8e3fb5,0xbec8bfb5,0x3ffb3f44,0x3f8e3fed,0x3ec8bfed,0x3fd53f44,
0xbff50000,0xbf710000,0x3f154000,0x3fe24000,0x3fa2bf8e,0xbfffbfd5,0xbfc6bfd5,0x3e493f8e,0xbe493fed,0xbfa2bfed,0x3fff3f44,0xbfc6bf44,
0xbf71bffb,0x3f15bec8,0xbfe23ec8,0xbff5bffb,0x3f444000,0x3fed4000,0x3fed0000,0x3f440000,0xbfedbfb5,0x3f443fb5,0xbf443fb5,0x3fed3fb5,
0x3fed0000,0xbf440000,0xbf44c000,0x3fed4000,0xbf443fb5,0xbfedbfb5,0x3fed3fb5,0x3f443fb5,0x3fe20000,0x3f150000,0xbf71c000,0xbff5c000,
0xbe493fd5,0x3fc63f8e,0x3fff3f8e,0xbfa2bfd5,0xbfc6bfed,0x3fff3fed,0xbfa23f44,0xbe49bf44,0x3ff53ec8,0x3fe23ffb,0xbf15bffb,0x3f713ec8,
0xbf8ec000,0xbffbc000,0xbfd50000,0xbec80000,0x3ffb3f44,0xbfd5bfed,0xbec8bfed,0xbf8ebf44,0xbec83fb5,0xbf8ebfb5,0x3ffb3fb5,0xbfd5bfb5,
0xbfd5bfed,0xbec8bf44,0xbf8e3f44,0xbffbbfed,0xbfc60000,0xbe490000,0x3fa24000,0x3fff4000,0xbf71bffb,0xbf15bec8,0xbfe2bec8,0x3ff53ffb,
0x3ff53f44,0xbf71bf44,0xbf15bfed,0x3fe23fed,0x3e493fd5,0xbfa2bf8e,0x3fff3f8e,0x3fc63fd5,0x40004000,0x3fb54000,0x0,0xbfb50000,
0x40004000,0xbfb50000,0x0,0xbfb5c000,0x40004000,0xbfb5c000,0x0,0x3fb50000,0x40004000,0x3fb50000,0x0,0x3fb54000,
0xbfc6bfb5,0xbfffbfb5,0xbfa2bfb5,0x3e49bfb5,0xbfe2bfd5,0x3f15bf8e,0xbf71bf8e,0x3ff53fd5,0xbff5bfed,0x3fe23fed,0xbf15bf44,0xbf713f44,
0xbfffbffb,0xbfa23ec8,0xbe49bec8,0xbfc6bffb,0x3ec80000,0x3fd50000,0x3ffb4000,0x3f8e4000,0x3f8e3f44,0x3ec83fed,0x3fd53fed,0xbffbbf44,
0x3fd53fb5,0xbffbbfb5,0x3f8e3fb5,0x3ec8bfb5,0x3ffb3fed,0x3f8ebf44,0x3ec83f44,0x3fd53fed,0x3f713fb5,0xbf153fb5,0xbfe2bfb5,0xbff5bfb5,
0xbe493ec8,0xbfa2bffb,0xbfffbffb,0x3fc6bec8,0xbfa2bf44,0x3fff3f44,0xbfc6bfed,0x3e493fed,0xbff5bfd5,0xbf713f8e,0xbf15bf8e,0xbfe2bfd5,
0xbfedc000,0xbf44c000,0x3f440000,0x3fed0000,0xbf44bfb5,0x3fed3fb5,0x3fed3fb5,0xbf443fb5,0x3f440000,0xbfed0000,0x3fed4000,0xbf44c000,
0x3fed3fb5,0x3f44bfb5,0x3f443fb5,0x3fed3fb5,0x3ff53fb5,0x3fe23fb5,0x3f153fb5,0xbf713fb5,0x3fc63ffb,0xbfffbec8,0xbfa2bec8,0xbe49bffb,
0xbe493f44,0x3fc6bf44,0xbfffbfed,0x3fa23fed,0xbfe2bf8e,0xbf153fd5,0xbf71bfd5,0xbff5bf8e,0xbf8e0000,0xbffb0000,0xbfd5c000,0xbec8c000,
0xbffbbfed,0x3fd5bf44,0x3ec8bf44,0x3f8e3fed,0xbec8bfb5,0xbf8e3fb5,0x3ffb3fb5,0xbfd5bfb5,0x3fd53f44,0x3ec8bfed,0x3f8e3fed,0x3ffb3f44,
0xbe49bfb5,0x3fa2bfb5,0x3fff3fb5,0x3fc63fb5,0x3ff53f8e,0xbf713fd5,0x3f153fd5,0xbfe2bf8e,0x3f713fed,0x3f15bfed,0xbfe2bf44,0x3ff53f44,
0xbfc6bec8,0xbe493ffb,0xbfa2bffb,0xbfffbec8,0x4000,0xbfb54000,0xc0000000,0xbfb50000,0xc000,0x3fb50000,0x40000000,0xbfb54000,
0x4000,0x3fb5c000,0xc0000000,0x3fb50000,0xc000,0xbfb50000,0x40000000,0x3fb5c000,0xbfa2bfb5,0x3e49bfb5,0x3fc6bfb5,0x3fffbfb5,
0x3f713fd5,0xbff53f8e,0xbfe23f8e,0x3f15bfd5,0xbf15bfed,0xbf713fed,0x3ff5bf44,0xbfe23f44,0x3e493ffb,0x3fc6bec8,0xbfff3ec8,0xbfa23ffb,
0x3ffb0000,0x3f8e0000,0xbec84000,0xbfd54000,0xbfd5bf44,0x3ffbbfed,0x3f8ebfed,0x3ec83f44,0x3f8e3fb5,0x3ec8bfb5,0xbfd53fb5,0x3ffbbfb5,
0xbec8bfed,0xbfd53f44,0x3ffbbf44,0x3f8ebfed,0xbfe23fb5,0xbff53fb5,0xbf71bfb5,0x3f15bfb5,0x3fffbec8,0xbfc63ffb,0xbe493ffb,0xbfa23ec8,
0xbfc6bf44,0x3e493f44,0x3fa2bfed,0xbfff3fed,0x3f153fd5,0x3fe2bf8e,0xbff53f8e,0xbf713fd5,0x3f44c000,0x3fedc000,0x3fed0000,0x3f440000,
0xbfed3fb5,0x3f44bfb5,0xbf44bfb5,0x3fedbfb5,0x3fed0000,0xbf440000,0xbf444000,0x3fedc000,0xbf44bfb5,0xbfed3fb5,0x3fedbfb5,0x3f44bfb5,
0x3f153fb5,0xbf713fb5,0xbff53fb5,0xbfe23fb5,0x3fa2bffb,0x3e493ec8,0x3fc63ec8,0xbfff3ffb,0xbfff3f44,0x3fa2bf44,0x3e49bfed,0xbfc63fed,
0x3f713f8e,0x3ff5bfd5,0xbfe23fd5,0xbf153f8e,0xbfd50000,0xbec80000,0x3f8ec000,0x3ffbc000,0xbec83fed,0xbf8e3f44,0xbffb3f44,0x3fd5bfed,
0x3ffbbfb5,0xbfd53fb5,0x3ec83fb5,0x3f8ebfb5,0xbf8ebf44,0xbffb3fed,0x3fd5bfed,0x3ec8bf44,0x3fffbfb5,0x3fc6bfb5,0x3e493fb5,0xbfa23fb5,
0xbf15bf8e,0x3fe2bfd5,0x3ff5bfd5,0xbf713f8e,0xbfe23fed,0x3ff5bfed,0xbf71bf44,0xbf153f44,0x3fa23ec8,0x3fffbffb,0xbfc63ffb,0xbe493ec8,
0xc0004000,0xbfb54000,0x0,0x3fb50000,0xc0004000,0x3fb50000,0x0,0x3fb5c000,0xc0004000,0x3fb5c000,0x0,0xbfb50000,
0xc0004000,0xbfb50000,0x0,0xbfb54000,0x3fc6bfb5,0x3fffbfb5,0x3fa2bfb5,0xbe49bfb5,0x3fe2bfd5,0xbf15bf8e,0x3f71bf8e,0xbff53fd5,
0x3ff5bfed,0xbfe23fed,0x3f15bf44,0x3f713f44,0x3fffbffb,0x3fa23ec8,0x3e49bec8,0x3fc6bffb,0xbec80000,0xbfd50000,0xbffb4000,0xbf8e4000,
0xbf8e3f44,0xbec83fed,0xbfd53fed,0x3ffbbf44,0xbfd53fb5,0x3ffbbfb5,0xbf8e3fb5,0xbec8bfb5,0xbffb3fed,0xbf8ebf44,0xbec83f44,0xbfd53fed,
0xbf713fb5,0x3f153fb5,0x3fe2bfb5,0x3ff5bfb5,0x3e493ec8,0x3fa2bffb,0x3fffbffb,0xbfc6bec8,0x3fa2bf44,0xbfff3f44,0x3fc6bfed,0xbe493fed,
0x3ff5bfd5,0x3f713f8e,0x3f15bf8e,0x3fe2bfd5,0x3fedc000,0x3f44c000,0xbf440000,0xbfed0000,0x3f44bfb5,0xbfed3fb5,0xbfed3fb5,0x3f443fb5,
0xbf440000,0x3fed0000,0xbfed4000,0x3f44c000,0xbfed3fb5,0xbf44bfb5,0xbf443fb5,0xbfed3fb5,0xbff53fb5,0xbfe23fb5,0xbf153fb5,0x3f713fb5,
0xbfc63ffb,0x3fffbec8,0x3fa2bec8,0x3e49bffb,0x3e493f44,0xbfc6bf44,0x3fffbfed,0xbfa23fed,0x3fe2bf8e,0x3f153fd5,0x3f71bfd5,0x3ff5bf8e,
0x3f8e0000,0x3ffb0000,0x3fd5c000,0x3ec8c000,0x3ffbbfed,0xbfd5bf44,0xbec8bf44,0xbf8e3fed,0x3ec8bfb5,0x3f8e3fb5,0xbffb3fb5,0x3fd5bfb5,
0xbfd53f44,0xbec8bfed,0xbf8e3fed,0xbffb3f44,0x3e49bfb5,0xbfa2bfb5,0xbfff3fb5,0xbfc63fb5,0xbff53f8e,0x3f713fd5,0xbf153fd5,0x3fe2bf8e,
0xbf713fed,0xbf15bfed,0x3fe2bf44,0xbff53f44,0x3fc6bec8,0x3e493ffb,0x3fa2bffb,0x3fffbec8,0x4000,0x3fb54000,0x40000000,0x3fb50000,
0xc000,0xbfb50000,0xc0000000,0x3fb54000,0x4000,0xbfb5c000,0x40000000,0xbfb50000,0xc000,0x3fb50000,0xc0000000,0xbfb5c000,
0x3fa2bfb5,0xbe49bfb5,0xbfc6bfb5,0xbfffbfb5,0xbf713fd5,0x3ff53f8e,0x3fe23f8e,0xbf15bfd5,0x3f15bfed,0x3f713fed,0xbff5bf44,0x3fe23f44,
0xbe493ffb,0xbfc6bec8,0x3fff3ec8,0x3fa23ffb,0xbffb0000,0xbf8e0000,0x3ec84000,0x3fd54000,0x3fd5bf44,0xbffbbfed,0xbf8ebfed,0xbec83f44,
0xbf8e3fb5,0xbec8bfb5,0x3fd53fb5,0xbffbbfb5,0x3ec8bfed,0x3fd53f44,0xbffbbf44,0xbf8ebfed,0x3fe23fb5,0x3ff53fb5,0x3f71bfb5,0xbf15bfb5,
0xbfffbec8,0x3fc63ffb,0x3e493ffb,0x3fa23ec8,0x3fc6bf44,0xbe493f44,0xbfa2bfed,0x3fff3fed,0xbf153fd5,0xbfe2bf8e,0x3ff53f8e,0x3f713fd5,
0xbf44c000,0xbfedc000,0xbfed0000,0xbf440000,0x3fed3fb5,0xbf44bfb5,0x3f44bfb5,0xbfedbfb5,0xbfed0000,0x3f440000,0x3f444000,0xbfedc000,
0x3f44bfb5,0x3fed3fb5,0xbfedbfb5,0xbf44bfb5,0xbf153fb5,0x3f713fb5,0x3ff53fb5,0x3fe23fb5,0xbfa2bffb,0xbe493ec8,0xbfc63ec8,0x3fff3ffb,
0x3fff3f44,0xbfa2bf44,0xbe49bfed,0x3fc63fed,0xbf713f8e,0xbff5bfd5,0x3fe23fd5,0x3f153f8e,0x3fd50000,0x3ec80000,0xbf8ec000,0xbffbc000,
0x3ec83fed,0x3f8e3f44,0x3ffb3f44,0xbfd5bfed,0xbffbbfb5,0x3fd53fb5,0xbec83fb5,0xbf8ebfb5,0x3f8ebf44,0x3ffb3fed,0xbfd5bfed,0xbec8bf44,
0xbfffbfb5,0xbfc6bfb5,0xbe493fb5,0x3fa23fb5,0x3f15bf8e,0xbfe2bfd5,0xbff5bfd5,0x3f713f8e,0x3fe23fed,0xbff5bfed,0x3f71bf44,0x3f153f44,
0xbfa23ec8,0xbfffbffb,0x3fc63ffb,0x3e493ec8,0x80003f80,0x3f800000,0x80003f80,0x3f800000,0x80003f80,0x3f800000,0x80003f80,0x3f800000,
0x80003f80,0x3f800000,0x80003f80,0x3f800000,0x80003f80,0x3f800000,0x80003f80,0x3f800000,0x80003f80,0x3f800000,0x8000bf80,0xbf800000,
0x3f353f35,0x3f35bf35,0xbf35bf35,0xbf353f35,0x3f800000,0xbf80,0xbf800000,0x3f80,0x3f35bf35,0xbf35bf35,0xbf353f35,0x3f353f35,
0x80003f80,0x3f800000,0x80003f80,0x3f800000,0x3f800000,0xbf80,0x3f800000,0xbf80,0x8000bf80,0xbf800000,0x8000bf80,0xbf800000,
0xbf800000,0x3f80,0xbf800000,0x3f80,0x80003f80,0x3f800000,0x8000bf80,0xbf800000,0x3f35bf35,0xbf35bf35,0xbf353f35,0x3f353f35,
0xbf800000,0x3f80,0x3f800000,0xbf80,0x3f353f35,0x3f35bf35,0xbf35bf35,0xbf353f35,0x80003f80,0x3f800000,0x80003f80,0x3f800000,
0x8000bf80,0xbf800000,0x8000bf80,0xbf800000,0x80003f80,0x3f800000,0x80003f80,0x3f800000,0x8000bf80,0xbf800000,0x8000bf80,0xbf800000,
0x80003f80,0x3f800000,0x8000bf80,0xbf800000,0xbf35bf35,0xbf353f35,0x3f353f35,0x3f35bf35,0x3f800000,0xbf80,0xbf800000,0x3f80,
0xbf353f35,0x3f353f35,0x3f35bf35,0xbf35bf35,0x80003f80,0x3f800000,0x80003f80,0x3f800000,0xbf800000,0x3f80,0xbf800000,0x3f80,
0x8000bf80,0xbf800000,0x8000bf80,0xbf800000,0x3f800000,0xbf80,0x3f800000,0xbf80,0x80003f80,0x3f800000,0x8000bf80,0xbf800000,
0xbf353f35,0x3f353f35,0x3f35bf35,0xbf35bf35,0xbf800000,0x3f80,0x3f800000,0xbf80,0xbf35bf35,0xbf353f35,0x3f353f35,0x3f35bf35,
0x3f803f80,0x80008000,0x80008000,0xbf80bf80,0x3f803f80,0x80008000,0x80008000,0xbf80bf80,0x3f803f80,0x80008000,0x80008000,0xbf80bf80,
0x3f803f80,0x80008000,0x80008000,0xbf80bf80,0x3f353f80,0x3f358000,0x3f358000,0xbf35bf80,0xbf350000,0x3f353f80,0x3f353f80,0x3f358000,
0xbf35bf80,0xbf358000,0xbf358000,0x3f353f80,0x3f350000,0xbf35bf80,0xbf35bf80,0xbf358000,0x3f80,0x3f808000,0x3f808000,0x8000bf80,
0xbf80,0xbf808000,0xbf808000,0x80003f80,0x3f80,0x3f808000,0x3f808000,0x8000bf80,0xbf80,0xbf808000,0xbf808000,0x80003f80,
0xbf353f80,0x3f358000,0x3f358000,0x3f35bf80,0x3f350000,0x3f35bf80,0x3f35bf80,0xbf358000,0x3f35bf80,0xbf358000,0xbf358000,0xbf353f80,
0xbf350000,0xbf353f80,0xbf353f80,0x3f358000,0xbf803f80,0x80008000,0x80008000,0x3f80bf80,0xbf803f80,0x80008000,0x80008000,0x3f80bf80,
0xbf803f80,0x80008000,0x80008000,0x3f80bf80,0xbf803f80,0x80008000,0x80008000,0x3f80bf80,0xbf353f80,0xbf358000,0xbf358000,0x3f35bf80,
0x3f350000,0xbf353f80,0xbf353f80,0xbf358000,0x3f35bf80,0x3f358000,0x3f358000,0xbf353f80,0xbf350000,0x3f35bf80,0x3f35bf80,0x3f358000,
0x3f80,0xbf808000,0xbf808000,0x8000bf80,0xbf80,0x3f808000,0x3f808000,0x80003f80,0x3f80,0xbf808000,0xbf808000,0x8000bf80,
0xbf80,0x3f808000,0x3f808000,0x80003f80,0x3f353f80,0xbf358000,0xbf358000,0xbf35bf80,0xbf350000,0xbf35bf80,0xbf35bf80,0x3f358000,
0xbf35bf80,0x3f358000,0x3f358000,0x3f353f80,0x3f350000,0x3f353f80,0x3f353f80,0xbf358000,0x3f800000,0x0,0x3f800000,0x0,
0x3f800000,0x0,0x3f800000,0x0,0x3f800000,0x0,0x3f800000,0x0,0x3f800000,0x0,0x3f800000,0x0,
0x3f800000,0x0,0x3f7fb10f,0xbd48fb30,0x3f7ec46d,0xbdc8bd36,0x3f7d3aac,0xbe164083,0x3f7b14be,0xbe47c5c2,0x3f7853f8,0xbe78cfcc,
0x3f74fa0b,0xbe94a031,0x3f710908,0xbeac7cd4,0x3f800000,0x0,0x3f7ec46d,0xbdc8bd36,0x3f7b14be,0xbe47c5c2,0x3f74fa0b,0xbe94a031,
0x3f6c835e,0xbec3ef15,0x3f61c598,0xbef15aea,0x3f54db31,0xbf0e39da,0x3f45e403,0xbf226799,0x3f800000,0x0,0x3f7d3aac,0xbe164083,
0x3f74fa0b,0xbe94a031,0x3f676bd8,0xbedae880,0x3f54db31,0xbf0e39da,0x3f3daef9,0xbf2beb4a,0x3f226799,0xbf45e403,0x3f039c3d,0xbf5b941a,
0x3f800000,0x0,0x3f7b14be,0xbe47c5c2,0x3f6c835e,0xbec3ef15,0x3f54db31,0xbf0e39da,0x3f3504f3,0xbf3504f3,0x3f0e39da,0xbf54db31,
0x3ec3ef15,0xbf6c835e,0x3e47c5c2,0xbf7b14be,0x3f800000,0x0,0x3f7853f8,0xbe78cfcc,0x3f61c598,0xbef15aea,0x3f3daef9,0xbf2beb4a,
0x3f0e39da,0xbf54db31,0x3eac7cd4,0xbf710908,0x3dc8bd36,0xbf7ec46d,0xbe164083,0xbf7d3aac,0x3f800000,0x0,0x3f74fa0b,0xbe94a031,
0x3f54db31,0xbf0e39da,0x3f226799,0xbf45e403,0x3ec3ef15,0xbf6c835e,0x3dc8bd36,0xbf7ec46d,0xbe47c5c2,0xbf7b14be,0xbef15aea,0xbf61c598,
0x3f800000,0x0,0x3f710908,0xbeac7cd4,0x3f45e403,0xbf226799,0x3f039c3d,0xbf5b941a,0x3e47c5c2,0xbf7b14be,0xbe164083,0xbf7d3aac,
0xbef15aea,0xbf61c598,0xbf3daef9,0xbf2beb4a,0x3f800000,0x0,0x3f800000,0x0,0x3f800000,0x0,0x3f800000,0x0,
0x3f800000,0x0,0x3f800000,0x0,0x3f800000,0x0,0x3f800000,0x0,0x3f6c835e,0xbec3ef15,0x3f676bd8,0xbedae880,
0x3f61c598,0xbef15aea,0x3f5b941a,0xbf039c3d,0x3f54db31,0xbf0e39da,0x3f4d9f02,0xbf187fc0,0x3f45e403,0xbf226799,0x3f3daef9,0xbf2beb4a,
0x3f3504f3,0xbf3504f3,0x3f226799,0xbf45e403,0x3f0e39da,0xbf54db31,0x3ef15aea,0xbf61c598,0x3ec3ef15,0xbf6c835e,0x3e94a031,0xbf74fa0b,
0x3e47c5c2,0xbf7b14be,0x3dc8bd36,0xbf7ec46d,0x3ec3ef15,0xbf6c835e,0x3e78cfcc,0xbf7853f8,0x3dc8bd36,0xbf7ec46d,0xbd48fb30,0xbf7fb10f,
0xbe47c5c2,0xbf7b14be,0xbeac7cd4,0xbf710908,0xbef15aea,0xbf61c598,0xbf187fc0,0xbf4d9f02,0x0,0xbf800000,0xbe47c5c2,0xbf7b14be,
0xbec3ef15,0xbf6c835e,0xbf0e39da,0xbf54db31,0xbf3504f3,0xbf3504f3,0xbf54db31,0xbf0e39da,0xbf6c835e,0xbec3ef15,0xbf7b14be,0xbe47c5c2,
0xbec3ef15,0xbf6c835e,0xbf187fc0,0xbf4d9f02,0xbf45e403,0xbf226799,0xbf676bd8,0xbedae880,0xbf7b14be,0xbe47c5c2,0xbf7fb10f,0x3d48fb30,
0xbf74fa0b,0x3e94a031,0xbf5b941a,0x3f039c3d,0xbf3504f3,0xbf3504f3,0xbf61c598,0xbef15aea,0xbf7b14be,0xbe47c5c2,0xbf7ec46d,0x3dc8bd36,
0xbf6c835e,0x3ec3ef15,0xbf45e403,0x3f226799,0xbf0e39da,0x3f54db31,0xbe94a031,0x3f74fa0b,0xbf6c835e,0xbec3ef15,0xbf7fb10f,0xbd48fb30,
0xbf74fa0b,0x3e94a031,0xbf4d9f02,0x3f187fc0,0xbf0e39da,0x3f54db31,0xbe78cfcc,0x3f7853f8,0x3dc8bd36,0x3f7ec46d,0x3edae880,0x3f676bd8,
0x80003f80,0x3f800000,0x3f800000,0xbf80,0x3ec43f6d,0x3f6dbec4,0x3f6dbec4,0xbec4bf6d,0x3f353f35,0x3f35bf35,0x3f35bf35,0xbf35bf35,
0x3f6d3ec4,0x3ec4bf6d,0x3ec4bf6d,0xbf6dbec4,0x80003f80,0x3f800000,0xbf800000,0x3f80,0x3f6d3ec4,0x3ec4bf6d,0xbec43f6d,0x3f6d3ec4,
0x3f35bf35,0xbf35bf35,0x3f353f35,0x3f35bf35,0xbec4bf6d,0xbf6d3ec4,0x3f6dbec4,0xbec4bf6d,0x80003f80,0x3f800000,0x3f800000,0xbf80,
0x3f6dbec4,0xbec4bf6d,0xbec4bf6d,0xbf6d3ec4,0xbf35bf35,0xbf353f35,0xbf353f35,0x3f353f35,0xbec43f6d,0x3f6d3ec4,0x3f6d3ec4,0x3ec4bf6d,
0x80003f80,0x3f800000,0xbf800000,0x3f80,0x3ec4bf6d,0xbf6dbec4,0x3f6d3ec4,0x3ec4bf6d,0xbf353f35,0x3f353f35,0xbf35bf35,0xbf353f35,
0x3f6dbec4,0xbec4bf6d,0x3ec43f6d,0x3f6dbec4,0x80003f80,0x3f800000,0x3f800000,0xbf80,0xbec4bf6d,0xbf6d3ec4,0xbf6d3ec4,0x3ec43f6d,
0x3f353f35,0x3f35bf35,0x3f35bf35,0xbf35bf35,0xbf6dbec4,0xbec43f6d,0xbec43f6d,0x3f6d3ec4,0x80003f80,0x3f800000,0xbf800000,0x3f80,
0xbf6dbec4,0xbec43f6d,0x3ec4bf6d,0xbf6dbec4,0x3f35bf35,0xbf35bf35,0x3f353f35,0x3f35bf35,0x3ec43f6d,0x3f6dbec4,0xbf6d3ec4,0x3ec43f6d,
0x80003f80,0x3f800000,0x3f800000,0xbf80,0xbf6d3ec4,0x3ec43f6d,0x3ec43f6d,0x3f6dbec4,0xbf35bf35,0xbf353f35,0xbf353f35,0x3f353f35,
0x3ec4bf6d,0xbf6dbec4,0xbf6dbec4,0xbec43f6d,0x80003f80,0x3f800000,0xbf800000,0x3f80,0xbec43f6d,0x3f6d3ec4,0xbf6dbec4,0xbec43f6d,
0xbf353f35,0x3f353f35,0xbf35bf35,0xbf353f35,0xbf6d3ec4,0x3ec43f6d,0xbec4bf6d,0xbf6d3ec4,0x3f803f80,0x80008000,0x80008000,0xbf80bf80,
0x3f803f80,0x80008000,0x80008000,0xbf80bf80,0x3f803f80,0x80008000,0x80008000,0xbf80bf80,0x3f803f80,0x80008000,0x80008000,0xbf80bf80,
0x3ec43f6d,0x3f6d3ec4,0x3f6d3ec4,0xbec4bf6d,0xbf6dbec4,0x3ec43f6d,0x3ec43f6d,0x3f6d3ec4,0xbec4bf6d,0xbf6dbec4,0xbf6dbec4,0x3ec43f6d,
0x3f6d3ec4,0xbec4bf6d,0xbec4bf6d,0xbf6dbec4,0xbf353f35,0x3f353f35,0x3f353f35,0x3f35bf35,0x3f35bf35,0xbf35bf35,0xbf35bf35,0xbf353f35,
0xbf353f35,0x3f353f35,0x3f353f35,0x3f35bf35,0x3f35bf35,0xbf35bf35,0xbf35bf35,0xbf353f35,0xbf6d3ec4,0xbec43f6d,0xbec43f6d,0x3f6dbec4,
0xbec43f6d,0x3f6dbec4,0x3f6dbec4,0x3ec4bf6d,0x3f6dbec4,0x3ec4bf6d,0x3ec4bf6d,0xbf6d3ec4,0x3ec4bf6d,0xbf6d3ec4,0xbf6d3ec4,0xbec43f6d,
0x0,0xbf803f80,0xbf803f80,0x80008000,0x0,0xbf803f80,0xbf803f80,0x80008000,0x0,0xbf803f80,0xbf803f80,0x80008000,
0x0,0xbf803f80,0xbf803f80,0x80008000,0x3f6dbec4,0xbec43f6d,0xbec43f6d,0xbf6d3ec4,0x3ec4bf6d,0x3f6dbec4,0x3f6dbec4,0xbec43f6d,
0xbf6d3ec4,0x3ec4bf6d,0x3ec4bf6d,0x3f6dbec4,0xbec43f6d,0xbf6d3ec4,0xbf6d3ec4,0x3ec4bf6d,0x3f35bf35,0x3f353f35,0x3f353f35,0xbf353f35,
0xbf353f35,0xbf35bf35,0xbf35bf35,0x3f35bf35,0x3f35bf35,0x3f353f35,0x3f353f35,0xbf353f35,0xbf353f35,0xbf35bf35,0xbf35bf35,0x3f35bf35,
0xbec4bf6d,0x3f6d3ec4,0x3f6d3ec4,0x3ec43f6d,0x3f6d3ec4,0x3ec43f6d,0x3ec43f6d,0xbf6dbec4,0x3ec43f6d,0xbf6dbec4,0xbf6dbec4,0xbec4bf6d,
0xbf6dbec4,0xbec4bf6d,0xbec4bf6d,0x3f6d3ec4,0x3f800000,0x0,0x3f7fec43,0xbcc90ab0,0x3f7fb10f,0xbd48fb30,0x3f7f4e6d,0xbd96a905,
0x3f7ec46d,0xbdc8bd36,0x3f7e1324,0xbdfab273,0x3f7d3aac,0xbe164083,0x3f7c3b28,0xbe2f10a2,0x3f800000,0x0,0x3f7f4e6d,0xbd96a905,
0x3f7d3aac,0xbe164083,0x3f79c79d,0xbe605c13,0x3f74fa0b,0xbe94a031,0x3f6ed89e,0xbeb8442a,0x3f676bd8,0xbedae880,0x3f5ebe05,0xbefc5d27,
0x3f800000,0x0,0x3f7e1324,0xbdfab273,0x3f7853f8,0xbe78cfcc,0x3f6ed89e,0xbeb8442a,0x3f61c598,0xbef15aea,0x3f514d3d,0xbf13682a,
0x3f3daef9,0xbf2beb4a,0x3f273656,0xbf41d870,0x3f800000,0x0,0x3f7c3b28,0xbe2f10a2,0x3f710908,0xbeac7cd4,0x3f5ebe05,0xbefc5d27,
0x3f45e403,0xbf226799,0x3f273656,0xbf41d870,0x3f039c3d,0xbf5b941a,0x3eb8442a,0xbf6ed89e,0x3f800000,0x0,0x3f79c79d,0xbe605c13,
0x3f676bd8,0xbedae880,0x3f49d112,0xbf1d7fd1,0x3f226799,0xbf45e403,0x3ee63375,0xbf64aa59,0x3e78cfcc,0xbf7853f8,0x3cc90ab0,0xbf7fec43,
0x3f800000,0x0,0x3f76ba07,0xbe888e93,0x3f5b941a,0xbf039c3d,0x3f3085bb,0xbf396842,0x3ef15aea,0xbf61c598,0x3e605c13,0xbf79c79d,
0xbd48fb30,0xbf7fb10f,0xbea09ae5,0xbf731447,0x3f800000,0x0,0x3f731447,0xbea09ae5,0x3f4d9f02,0xbf187fc0,0x3f13682a,0xbf514d3d,
0x3e94a031,0xbf74fa0b,0xbcc90ab0,0xbf7fec43,0xbeac7cd4,0xbf710908,0xbf1d7fd1,0xbf49d112,0x3f800000,0x0,0x3f6ed89e,0xbeb8442a,
0x3f3daef9,0xbf2beb4a,0x3ee63375,0xbf64aa59,0x3dc8bd36,0xbf7ec46d,0xbe888e93,0xbf76ba07,0xbf187fc0,0xbf4d9f02,0xbf584853,0xbf08f59b,
0x3f7b14be,0xbe47c5c2,0x3f79c79d,0xbe605c13,0x3f7853f8,0xbe78cfcc,0x3f76ba07,0xbe888e93,0x3f74fa0b,0xbe94a031,0x3f731447,0xbea09ae5,
0x3f710908,0xbeac7cd4,0x3f6ed89e,0xbeb8442a,0x3f54db31,0xbf0e39da,0x3f49d112,0xbf1d7fd1,0x3f3daef9,0xbf2beb4a,0x3f3085bb,0xbf396842,
0x3f226799,0xbf45e403,0x3f13682a,0xbf514d3d,0x3f039c3d,0xbf5b941a,0x3ee63375,0xbf64aa59,0x3f0e39da,0xbf54db31,0x3ee63375,0xbf64aa59,
0x3eac7cd4,0xbf710908,0x3e605c13,0xbf79c79d,0x3dc8bd36,0xbf7ec46d,0xbcc90ab0,0xbf7fec43,0xbe164083,0xbf7d3aac,0xbe888e93,0xbf76ba07,
0x3e47c5c2,0xbf7b14be,0x3cc90ab0,0xbf7fec43,0xbe164083,0xbf7d3aac,0xbea09ae5,0xbf731447,0xbef15aea,0xbf61c598,0xbf1d7fd1,0xbf49d112,
0xbf3daef9,0xbf2beb4a,0xbf584853,0xbf08f59b,0xbe47c5c2,0xbf7b14be,0xbecf7bca,0xbf6a09a7,0xbf187fc0,0xbf4d9f02,0xbf41d870,0xbf273656,
0xbf61c598,0xbef15aea,0xbf76ba07,0xbe888e93,0xbf7fb10f,0xbd48fb30,0xbf7c3b28,0x3e2f10a2,0xbf0e39da,0xbf54db31,0xbf41d870,0xbf273656,
0xbf676bd8,0xbedae880,0xbf7c3b28,0xbe2f10a2,0xbf7ec46d,0x3dc8bd36,0xbf6ed89e,0x3eb8442a,0xbf4d9f02,0x3f187fc0,0xbf1d7fd1,0x3f49d112,
0xbf54db31,0xbf0e39da,0xbf76ba07,0xbe888e93,0xbf7fb10f,0x3d48fb30,0xbf6ed89e,0x3eb8442a,0xbf45e403,0x3f226799,0xbf08f59b,0x3f584853,
0xbe78cfcc,0x3f7853f8,0x3d96a905,0x3f7f4e6d,0xbf7b14be,0xbe47c5c2,0xbf7c3b28,0x3e2f10a2,0xbf5b941a,0x3f039c3d,0xbf1d7fd1,0x3f49d112,
0xbe94a031,0x3f74fa0b,0x3d96a905,0x3f7f4e6d,0x3edae880,0x3f676bd8,0x3f396842,0x3f3085bb,0x80003f80,0x80003f80,0x80003f80,0x80003f80,
0x80003f80,0x80003f80,0x80003f80,0x80003f80,0x80003f80,0x80003f80,0x80003f80,0x80003f80,0x80003f80,0x80003f80,0x80003f80,0x80003f80,
0x3f800000,0x3f800000,0x3f800000,0x3f800000,0x3f800000,0x3f800000,0x3f800000,0x3f800000,0x3f800000,0x3f800000,0x3f800000,0x3f800000,
0x3f800000,0x3f800000,0x3f800000,0x3f800000,0x80003f80,0x3f353f35,0x80003f80,0x3f353f35,0x3f800000,0x3f35bf35,0x3f800000,0x3f35bf35,
0x8000bf80,0xbf35bf35,0x8000bf80,0xbf35bf35,0xbf800000,0xbf353f35,0xbf800000,0xbf353f35,0x3f800000,0x3f35bf35,0x3f800000,0x3f35bf35,
0xbf80,0xbf35bf35,0xbf80,0xbf35bf35,0xbf800000,0xbf353f35,0xbf800000,0xbf353f35,0x3f80,0x3f353f35,0x3f80,0x3f353f35,
0x80003f80,0x3f800000,0x80003f80,0x3f800000,0x8000bf80,0xbf800000,0x8000bf80,0xbf800000,0x80003f80,0x3f800000,0x80003f80,0x3f800000,
0x8000bf80,0xbf800000,0x8000bf80,0xbf800000,0x3f800000,0xbf80,0x3f800000,0xbf80,0xbf800000,0x3f80,0xbf800000,0x3f80,
0x3f800000,0xbf80,0x3f800000,0xbf80,0xbf800000,0x3f80,0xbf800000,0x3f80,0x80003f80,0x3f35bf35,0x80003f80,0x3f35bf35,
0xbf800000,0x3f353f35,0xbf800000,0x3f353f35,0x8000bf80,0xbf353f35,0x8000bf80,0xbf353f35,0x3f800000,0xbf35bf35,0x3f800000,0xbf35bf35,
0x3f800000,0xbf35bf35,0x3f800000,0xbf35bf35,0x3f80,0x3f35bf35,0x3f80,0x3f35bf35,0xbf800000,0x3f353f35,0xbf800000,0x3f353f35,
0xbf80,0xbf353f35,0xbf80,0xbf353f35,0x80003f80,0x3ec43f6d,0x8000bf80,0xbec4bf6d,0x3f353f35,0x3f6d3ec4,0xbf35bf35,0xbf6dbec4,
0x3f800000,0x3f6dbec4,0xbf800000,0xbf6d3ec4,0x3f35bf35,0x3ec4bf6d,0xbf353f35,0xbec43f6d,0x3f800000,0x3f6dbec4,0xbf800000,0xbf6d3ec4,
0x3f35bf35,0x3ec4bf6d,0xbf353f35,0xbec43f6d,0xbf80,0xbec4bf6d,0x3f80,0x3ec43f6d,0xbf35bf35,0xbf6dbec4,0x3f353f35,0x3f6d3ec4,
0x80003f80,0x3f6d3ec4,0x8000bf80,0xbf6dbec4,0x3f35bf35,0xbec4bf6d,0xbf353f35,0x3ec43f6d,0xbf800000,0xbec43f6d,0x3f800000,0x3ec4bf6d,
0x3f353f35,0x3f6dbec4,0xbf35bf35,0xbf6d3ec4,0x3f800000,0x3ec4bf6d,0xbf800000,0xbec43f6d,0xbf35bf35,0xbf6d3ec4,0x3f353f35,0x3f6dbec4,
0x3f80,0x3f6d3ec4,0xbf80,0xbf6dbec4,0x3f35bf35,0xbec4bf6d,0xbf353f35,0x3ec43f6d,0x80003f80,0x3f6dbec4,0x8000bf80,0xbf6d3ec4,
0xbf35bf35,0xbec43f6d,0x3f353f35,0x3ec4bf6d,0x3f800000,0xbec4bf6d,0xbf800000,0x3ec43f6d,0xbf353f35,0x3f6d3ec4,0x3f35bf35,0xbf6dbec4,
0x3f800000,0xbec4bf6d,0xbf800000,0x3ec43f6d,0xbf353f35,0x3f6d3ec4,0x3f35bf35,0xbf6dbec4,0xbf80,0xbf6d3ec4,0x3f80,0x3f6dbec4,
0x3f353f35,0x3ec4bf6d,0xbf35bf35,0xbec43f6d,0x80003f80,0x3ec4bf6d,0x8000bf80,0xbec43f6d,0xbf353f35,0x3f6dbec4,0x3f35bf35,0xbf6d3ec4,
0xbf800000,0x3f6d3ec4,0x3f800000,0xbf6dbec4,0xbf35bf35,0x3ec43f6d,0x3f353f35,0xbec4bf6d,0x3f800000,0xbf6dbec4,0xbf800000,0x3f6d3ec4,
0x3f353f35,0xbec4bf6d,0xbf35bf35,0x3ec43f6d,0x3f80,0x3ec4bf6d,0xbf80,0xbec43f6d,0xbf353f35,0x3f6dbec4,0x3f35bf35,0xbf6d3ec4,
0x80003f80,0x8000bf80,0x80003f80,0x8000bf80,0x80003f80,0x8000bf80,0x80003f80,0x8000bf80,0x80003f80,0x8000bf80,0x80003f80,0x8000bf80,
0x80003f80,0x8000bf80,0x80003f80,0x8000bf80,0x3f800000,0xbf800000,0x3f800000,0xbf800000,0x3f800000,0xbf800000,0x3f800000,0xbf800000,
0x3f800000,0xbf800000,0x3f800000,0xbf800000,0x3f800000,0xbf800000,0x3f800000,0xbf800000,0x80003f80,0xbf35bf35,0x80003f80,0xbf35bf35,
0x3f800000,0xbf353f35,0x3f800000,0xbf353f35,0x8000bf80,0x3f353f35,0x8000bf80,0x3f353f35,0xbf800000,0x3f35bf35,0xbf800000,0x3f35bf35,
0x3f800000,0xbf353f35,0x3f800000,0xbf353f35,0xbf80,0x3f353f35,0xbf80,0x3f353f35,0xbf800000,0x3f35bf35,0xbf800000,0x3f35bf35,
0x3f80,0xbf35bf35,0x3f80,0xbf35bf35,0x80003f80,0xbf800000,0x80003f80,0xbf800000,0x8000bf80,0x3f800000,0x8000bf80,0x3f800000,
0x80003f80,0xbf800000,0x80003f80,0xbf800000,0x8000bf80,0x3f800000,0x8000bf80,0x3f800000,0x3f800000,0x3f80,0x3f800000,0x3f80,
0xbf800000,0xbf80,0xbf800000,0xbf80,0x3f800000,0x3f80,0x3f800000,0x3f80,0xbf800000,0xbf80,0xbf800000,0xbf80,
0x80003f80,0xbf353f35,0x80003f80,0xbf353f35,0xbf800000,0xbf35bf35,0xbf800000,0xbf35bf35,0x8000bf80,0x3f35bf35,0x8000bf80,0x3f35bf35,
0x3f800000,0x3f353f35,0x3f800000,0x3f353f35,0x3f800000,0x3f353f35,0x3f800000,0x3f353f35,0x3f80,0xbf353f35,0x3f80,0xbf353f35,
0xbf800000,0xbf35bf35,0xbf800000,0xbf35bf35,0xbf80,0x3f35bf35,0xbf80,0x3f35bf35,0x80003f80,0xbec4bf6d,0x8000bf80,0x3ec43f6d,
0x3f353f35,0xbf6dbec4,0xbf35bf35,0x3f6d3ec4,0x3f800000,0xbf6d3ec4,0xbf800000,0x3f6dbec4,0x3f35bf35,0xbec43f6d,0xbf353f35,0x3ec4bf6d,
0x3f800000,0xbf6d3ec4,0xbf800000,0x3f6dbec4,0x3f35bf35,0xbec43f6d,0xbf353f35,0x3ec4bf6d,0xbf80,0x3ec43f6d,0x3f80,0xbec4bf6d,
0xbf35bf35,0x3f6d3ec4,0x3f353f35,0xbf6dbec4,0x80003f80,0xbf6dbec4,0x8000bf80,0x3f6d3ec4,0x3f35bf35,0x3ec43f6d,0xbf353f35,0xbec4bf6d,
0xbf800000,0x3ec4bf6d,0x3f800000,0xbec43f6d,0x3f353f35,0xbf6d3ec4,0xbf35bf35,0x3f6dbec4,0x3f800000,0xbec43f6d,0xbf800000,0x3ec4bf6d,
0xbf35bf35,0x3f6dbec4,0x3f353f35,0xbf6d3ec4,0x3f80,0xbf6dbec4,0xbf80,0x3f6d3ec4,0x3f35bf35,0x3ec43f6d,0xbf353f35,0xbec4bf6d,
0x80003f80,0xbf6d3ec4,0x8000bf80,0x3f6dbec4,0xbf35bf35,0x3ec4bf6d,0x3f353f35,0xbec43f6d,0x3f800000,0x3ec43f6d,0xbf800000,0xbec4bf6d,
0xbf353f35,0xbf6dbec4,0x3f35bf35,0x3f6d3ec4,0x3f800000,0x3ec43f6d,0xbf800000,0xbec4bf6d,0xbf353f35,0xbf6dbec4,0x3f35bf35,0x3f6d3ec4,
0xbf80,0x3f6dbec4,0x3f80,0xbf6d3ec4,0x3f353f35,0xbec43f6d,0xbf35bf35,0x3ec4bf6d,0x80003f80,0xbec43f6d,0x8000bf80,0x3ec4bf6d,
0xbf353f35,0xbf6d3ec4,0x3f35bf35,0x3f6dbec4,0xbf800000,0xbf6dbec4,0x3f800000,0x3f6d3ec4,0xbf35bf35,0xbec4bf6d,0x3f353f35,0x3ec43f6d,
0x3f800000,0x3f6d3ec4,0xbf800000,0xbf6dbec4,0x3f353f35,0x3ec43f6d,0xbf35bf35,0xbec4bf6d,0x3f80,0xbec43f6d,0xbf80,0x3ec4bf6d,
0xbf353f35,0xbf6d3ec4,0x3f35bf35,0x3f6dbec4,
};
constexpr int TB_F = 0, TB_E = 512, TB_P2 = 1024;

enum { C_EP = 0, C_Z1 = 32, C_Z2 = 96, C_H3 = 128, C_U = 160, C_X = 288, C_TOTAL = 512 };
struct Scratch {
  unsigned cnt[C_TOTAL];
  uint32_t moda[8 * 2 * D_];
  uint32_t mod[4 * D_ + 256];
  uint32_t z1[120 * 5120];
  uint32_t z2[128 * 4800];
  uint8_t h3[32 * 18 * 4096];
  uint8_t u[72 * D_ * 128];
};
__device__ __align__(1024) Scratch g_s;

#define PF2 8
#define PF2K 16
#define HOLDA 5
#define GOAT 0
#define H3W 0
#define X1K 10
#define PEEK 1
#ifndef NV1
#define NV1 12
#endif
#ifndef NV2
#define NV2 20
#endif
#define GDEP 0
#define TRK0 50
#define W0N 3
#define TRKC 350
#define J2 6
#define MODPOS 2
#define LNM 0x30
constexpr int NB15 = 192 + 32 * __builtin_popcount(LNM);
#define HD1 200
#define NG1 1

#define FAILCNT(k) do {} while (0)
#define CK(k) do {} while (0)
#define CKX(k) do {} while (0)
#define TS(k) do {} while (0)
#define TSC(k) do {} while (0)
struct Maps { CUtensorMap z1, z2[2], w1a, w1b, h3, w2, wf[4], wm; };
struct Params {
  const __nv_bfloat16 *x, *c, *wmod;
  Scratch* s;
  const uint4* tab;
  const __nv_bfloat16 *wr, *wi, *w1, *w2, *b1, *b2;
  uint32_t* out;
};

__device__ __forceinline__ uint32_t smem_u32(const void* p) { return (uint32_t)__cvta_generic_to_shared(p); }
__device__ __forceinline__ void mbar_init(uint32_t b, int c) { asm volatile("mbarrier.init.shared::cta.b64 [%0], %1;" ::"r"(b), "r"(c)); }
__device__ __forceinline__ void mbar_expect(uint32_t b, int bytes) { asm volatile("mbarrier.arrive.expect_tx.shared::cta.b64 _, [%0], %1;" ::"r"(b), "r"(bytes) : "memory"); }
__device__ __forceinline__ void mbar_arrive(uint32_t b) { asm volatile("mbarrier.arrive.shared::cta.b64 _, [%0];" ::"r"(b) : "memory"); }
#define MBAR_WAIT(SEM)                                                                                                         \
  asm volatile("{\n.reg .pred p;\n.reg .u32 it;\nmov.u32 it, 0;\nW:\nmbarrier.try_wait.parity" SEM ".shared::cta.b64 p, [%0], %1;\n" \
               "@p bra.uni D;\nadd.u32 it, it, 1;\nsetp.lt.u32 p, it, 0x400000;\n@p bra.uni W;\ntrap;\nD:\n}" ::"r"(b), "r"(ph) : "memory")
__device__ __forceinline__ void mbar_wait(uint32_t b, int ph) { MBAR_WAIT(""); }
__device__ __forceinline__ uint32_t mbar_test(uint32_t b, int ph) {
  uint32_t ok;
  asm volatile("{\n.reg .pred p;\nmbarrier.test_wait.parity.shared::cta.b64 p, [%1], %2;\nselp.u32 %0, 1, 0, p;\n}\n" : "=r"(ok) : "r"(b), "r"(ph) : "memory");
  return ok;
}
__device__ __forceinline__ void tma2d(uint32_t dst, const CUtensorMap* m, int c0, int c1, uint32_t bar) {
  asm volatile("cp.async.bulk.tensor.2d.shared::cluster.global.mbarrier::complete_tx::bytes [%0], [%1, {%3, %4}], [%2];" ::"r"(dst), "l"(m), "r"(bar), "r"(c0), "r"(c1) : "memory");
}
__device__ __forceinline__ uint64_t pol_ef() { uint64_t p; asm("createpolicy.fractional.L2::evict_first.b64 %0, 1.0;" : "=l"(p)); return p; }
__device__ __forceinline__ void tma3d_ef(uint32_t dst, const CUtensorMap* m, int c1, int c2, uint32_t bar) {
  asm volatile("cp.async.bulk.tensor.3d.shared::cluster.global.mbarrier::complete_tx::bytes.L2::cache_hint [%0], [%1, {%3, %4, %5}], [%2], %6;" ::"r"(dst), "l"(m), "r"(bar), "r"(0), "r"(c1), "r"(c2), "l"(pol_ef()) : "memory");
}
__device__ __forceinline__ void tma4d_ef(uint32_t dst, const CUtensorMap* m, int c1, int c2, int c3, uint32_t bar) {
  asm volatile("cp.async.bulk.tensor.4d.shared::cluster.global.mbarrier::complete_tx::bytes.L2::cache_hint [%0], [%1, {%3, %7, %4, %5}], [%2], %6;" ::"r"(dst), "l"(m), "r"(bar), "r"(0), "r"(c2), "r"(c3), "l"(pol_ef()), "r"(c1) : "memory");
}
__device__ __forceinline__ void bulk_ld(uint32_t dst, const void* src, int bytes, uint32_t bar) {
  asm volatile("cp.async.bulk.shared::cluster.global.mbarrier::complete_tx::bytes [%0], [%1], %2, [%3];" ::"r"(dst), "l"(src), "r"(bytes), "r"(bar) : "memory");
}
__device__ __forceinline__ void bulk_st(void* dst, uint32_t src, int bytes) {
  asm volatile("cp.async.bulk.global.shared::cta.bulk_group [%0], [%1], %2;" ::"l"(dst), "r"(src), "r"(bytes) : "memory");
}
__device__ __forceinline__ void tma_st2d(const CUtensorMap* m, uint32_t src, int c0, int c1) {
  asm volatile("cp.async.bulk.tensor.2d.global.shared::cta.bulk_group [%0, {%2, %3}], [%1];" ::"l"(m), "r"(src), "r"(c0), "r"(c1) : "memory");
}
__device__ __forceinline__ void tma_st3d(const CUtensorMap* m, uint32_t src, int c0, int c1, int c2) {
  asm volatile("cp.async.bulk.tensor.3d.global.shared::cta.bulk_group [%0, {%2, %3, %4}], [%1];" ::"l"(m), "r"(src), "r"(c0), "r"(c1), "r"(c2) : "memory");
}
__device__ __forceinline__ void bulk_commit_wait_read() {
  asm volatile("cp.async.bulk.commit_group;" ::: "memory");
  asm volatile("cp.async.bulk.wait_group.read 0;" ::: "memory");
}
__device__ __forceinline__ void bulk_commit_wait() {
  asm volatile("cp.async.bulk.commit_group;" ::: "memory");
  asm volatile("cp.async.bulk.wait_group 0;" ::: "memory");
}
__device__ __forceinline__ void prefetch_l2(const void* p, int bytes) {
  asm volatile("cp.async.bulk.prefetch.L2.global [%0], %1;" ::"l"(p), "r"(bytes) : "memory");
}
__device__ __forceinline__ void wg_fence() { asm volatile("wgmma.fence.sync.aligned;" ::: "memory"); }
__device__ __forceinline__ void wg_commit() { asm volatile("wgmma.commit_group.sync.aligned;" ::: "memory"); }
template <int N> __device__ __forceinline__ void wg_wait() { asm volatile("wgmma.wait_group.sync.aligned %0;" ::"n"(N) : "memory"); }
template <int N> __device__ __forceinline__ void reg_fence(float (&d)[N]) {
#pragma unroll
  for (int i = 0; i < N; i++) asm volatile("" : "+f"(d[i])::"memory");
}
__device__ __forceinline__ void fence_async_smem() { asm volatile("fence.proxy.async.shared::cta;" ::: "memory"); }
__device__ __forceinline__ void fence_async_glb() { asm volatile("fence.proxy.async.global;" ::: "memory"); }
__device__ __forceinline__ uint32_t ld_rlx(const void* p) { uint32_t v; asm volatile("ld.relaxed.gpu.global.b32 %0, [%1];" : "=r"(v) : "l"(p) : "memory"); return v; }
__device__ __forceinline__ uint2 ld_rlx2(const void* p) { uint2 v; asm volatile("ld.relaxed.gpu.global.v2.b32 {%0,%1}, [%2];" : "=r"(v.x), "=r"(v.y) : "l"(p) : "memory"); return v; }
__device__ __forceinline__ uint4 ld_rlx4(const void* p) { uint4 v; asm volatile("ld.relaxed.gpu.global.v4.b32 {%0,%1,%2,%3}, [%4];" : "=r"(v.x), "=r"(v.y), "=r"(v.z), "=r"(v.w) : "l"(p) : "memory"); return v; }
__device__ __forceinline__ uint32_t ld_nc(const void* p) { uint32_t v; asm volatile("ld.global.nc.L1::no_allocate.b32 %0, [%1];" : "=r"(v) : "l"(p) : "memory"); return v; }
__device__ __forceinline__ uint4 ld_nc4(const void* p) { uint4 v; asm volatile("ld.global.nc.v4.b32 {%0,%1,%2,%3}, [%4];" : "=r"(v.x), "=r"(v.y), "=r"(v.z), "=r"(v.w) : "l"(p) : "memory"); return v; }
__device__ __forceinline__ uint32_t lds(uint32_t a) { uint32_t v; asm volatile("ld.shared.b32 %0, [%1];" : "=r"(v) : "r"(a) : "memory"); return v; }
__device__ __forceinline__ uint2 lds2(uint32_t a) { uint2 v; asm volatile("ld.shared.v2.b32 {%0,%1}, [%2];" : "=r"(v.x), "=r"(v.y) : "r"(a) : "memory"); return v; }
__device__ __forceinline__ uint4 lds4(uint32_t a) { uint4 v; asm volatile("ld.shared.v4.b32 {%0,%1,%2,%3}, [%4];" : "=r"(v.x), "=r"(v.y), "=r"(v.z), "=r"(v.w) : "r"(a) : "memory"); return v; }
__device__ __forceinline__ float lds_bf(uint32_t a) { uint32_t v; asm volatile("ld.shared.u16 %0, [%1];" : "=r"(v) : "r"(a) : "memory"); return __uint_as_float(v << 16); }
__device__ __forceinline__ void sts(uint32_t a, uint32_t v) { asm volatile("st.shared.b32 [%0], %1;" ::"r"(a), "r"(v) : "memory"); }
__device__ __forceinline__ void sts2(uint32_t a, uint32_t v0, uint32_t v1) { asm volatile("st.shared.v2.b32 [%0], {%1,%2};" ::"r"(a), "r"(v0), "r"(v1) : "memory"); }
__device__ __forceinline__ void sts4(uint32_t a, uint32_t v0, uint32_t v1, uint32_t v2, uint32_t v3) { asm volatile("st.shared.v4.b32 [%0], {%1,%2,%3,%4};" ::"r"(a), "r"(v0), "r"(v1), "r"(v2), "r"(v3) : "memory"); }
__device__ __forceinline__ void bar_sync(int id, int n) { asm volatile("bar.sync %0, %1;" ::"r"(id), "r"(n) : "memory"); }
__device__ __forceinline__ void bar_arrive(int id, int n) { asm volatile("bar.arrive %0, %1;" ::"r"(id), "r"(n) : "memory"); }
__device__ __forceinline__ void red_add(unsigned* p, unsigned v) { asm volatile("red.relaxed.gpu.global.add.u32 [%0], %1;" ::"l"(p), "r"(v) : "memory"); }
__device__ __forceinline__ bool any(bool p) { return __any_sync(0xffffffffu, p); }
__device__ __forceinline__ void pause(unsigned clks) {
  asm volatile("{\n.reg .pred p;\n.reg .u32 a, b;\nmov.u32 a, %%clock;\nW:\nmov.u32 b, %%clock;\nsub.u32 b, b, a;\nsetp.lt.s32 p, b, %0;\n@p bra.uni W;\n}" ::"r"(clks) : "memory");
}
__device__ __forceinline__ void red_bf16x8(uint32_t* p, uint32_t a, uint32_t b, uint32_t c, uint32_t d) {
  asm volatile("red.relaxed.gpu.global.add.noftz.v4.bf16x2 [%0], {%1,%2,%3,%4};" ::"l"(p), "r"(a), "r"(b), "r"(c), "r"(d) : "memory");
}
__device__ __forceinline__ void red_bf16x4(uint32_t* p, uint32_t a, uint32_t b) {
  asm volatile("red.relaxed.gpu.global.add.noftz.v2.bf16x2 [%0], {%1,%2};" ::"l"(p), "r"(a), "r"(b) : "memory");
}
constexpr int SPIN_MAX = 1 << 20;
__device__ __forceinline__ uint32_t ld_acq(const void* p) { uint32_t v; asm volatile("ld.acquire.gpu.global.b32 %0, [%1];" : "=r"(v) : "l"(p) : "memory"); return v; }
template <bool ACQ = false> __device__ __forceinline__ void wait_cnt(const unsigned* p, unsigned target) {
  int it = 0;
  while (any((int)((ACQ ? ld_acq(p) : ld_rlx(p)) - target) < 0) && ++it < SPIN_MAX) {}
}
__device__ __forceinline__ uint32_t pack_bf16(float lo, float hi) { uint32_t r; asm("cvt.rn.bf16x2.f32 %0, %1, %2;" : "=r"(r) : "f"(hi), "f"(lo)); return r; }
__device__ __forceinline__ float bf_lo(uint32_t v) { return __uint_as_float(v << 16); }
__device__ __forceinline__ float bf_hi(uint32_t v) { return __uint_as_float(v & 0xffff0000u); }
__device__ __forceinline__ uint32_t hadd2(uint32_t a, uint32_t b) { uint32_t r; asm("add.rn.bf16x2 %0, %1, %2;" : "=r"(r) : "r"(a), "r"(b)); return r; }
__device__ __forceinline__ uint32_t hmul2(uint32_t a, uint32_t b) { uint32_t r; asm("mul.rn.bf16x2 %0, %1, %2;" : "=r"(r) : "r"(a), "r"(b)); return r; }
__device__ __forceinline__ uint32_t hfma2(uint32_t a, uint32_t b, uint32_t c) { uint32_t r; asm("fma.rn.bf16x2 %0, %1, %2, %3;" : "=r"(r) : "r"(a), "r"(b), "r"(c)); return r; }
__device__ __forceinline__ float rbf(float x) { uint32_t r; asm("cvt.rn.bf16x2.f32 %0, %1, %2;" : "=r"(r) : "f"(x), "f"(0.0f)); return __uint_as_float(r); }
__device__ __forceinline__ void stmatrix4(uint32_t a, uint32_t r0, uint32_t r1, uint32_t r2, uint32_t r3) {
  asm volatile("stmatrix.sync.aligned.m8n8.x4.shared.b16 [%0], {%1,%2,%3,%4};" ::"r"(a), "r"(r0), "r"(r1), "r"(r2), "r"(r3) : "memory");
}
__device__ __forceinline__ void stmatrix2(uint32_t a, uint32_t r0, uint32_t r1) {
  asm volatile("stmatrix.sync.aligned.m8n8.x2.shared.b16 [%0], {%1,%2};" ::"r"(a), "r"(r0), "r"(r1) : "memory");
}
__device__ __forceinline__ void stmatrix4t(uint32_t a, uint32_t r0, uint32_t r1, uint32_t r2, uint32_t r3) {
  asm volatile("stmatrix.sync.aligned.m8n8.x4.trans.shared.b16 [%0], {%1,%2,%3,%4};" ::"r"(a), "r"(r0), "r"(r1), "r"(r2), "r"(r3) : "memory");
}
__device__ __forceinline__ uint32_t movm(uint32_t a) { uint32_t r; asm("movmatrix.sync.aligned.m8n8.trans.b16 %0, %1;" : "=r"(r) : "r"(a)); return r; }
template <bool ACC> __device__ __forceinline__ void mma16(float* d, uint32_t a0, uint32_t a1, uint32_t a2, uint32_t a3, uint32_t b0, uint32_t b1) {
  if (ACC) asm("mma.sync.aligned.m16n8k16.row.col.f32.bf16.bf16.f32 {%0,%1,%2,%3}, {%4,%5,%6,%7}, {%8,%9}, {%0,%1,%2,%3};"
               : "+f"(d[0]), "+f"(d[1]), "+f"(d[2]), "+f"(d[3]) : "r"(a0), "r"(a1), "r"(a2), "r"(a3), "r"(b0), "r"(b1));
  else asm("mma.sync.aligned.m16n8k16.row.col.f32.bf16.bf16.f32 {%0,%1,%2,%3}, {%4,%5,%6,%7}, {%8,%9}, {%10,%10,%10,%10};"
           : "=f"(d[0]), "=f"(d[1]), "=f"(d[2]), "=f"(d[3]) : "r"(a0), "r"(a1), "r"(a2), "r"(a3), "r"(b0), "r"(b1), "f"(0.f));
}
__device__ __forceinline__ uint32_t pin(uint32_t v) { uint32_t r; asm volatile("shfl.sync.bfly.b32 %0, %1, 0, 31, 0xffffffff;" : "=r"(r) : "r"(v)); return r; }
template <class T> __device__ __forceinline__ T* pin(T* p) {
  const uint64_t a = reinterpret_cast<uint64_t>(p);
  return reinterpret_cast<T*>((uint64_t)pin((uint32_t)a) | ((uint64_t)pin((uint32_t)(a >> 32)) << 32));
}
__device__ __forceinline__ uint32_t upin(uint32_t v) { return __shfl_sync(0xffffffffu, v, 0); }
template <class T> __device__ __forceinline__ T* upin(T* p) {
  const uint64_t a = reinterpret_cast<uint64_t>(p);
  return reinterpret_cast<T*>((uint64_t)upin((uint32_t)a) | ((uint64_t)upin((uint32_t)(a >> 32)) << 32));
}
__device__ __forceinline__ bool elect() {
  uint32_t p;
  asm volatile("{\n.reg .pred P;\nelect.sync _|P, 0xffffffff;\nselp.u32 %0, 1, 0, P;\n}" : "=r"(p));
  return p;
}
__device__ __forceinline__ uint32_t set_tag(uint32_t w, uint32_t tag) { uint32_t r; asm("lop3.b32 %0, %1, 0xfffffffe, %2, 0xea;" : "=r"(r) : "r"(w), "r"(tag)); return r; }
__device__ __forceinline__ uint32_t bitsel(uint32_t w, uint32_t m, uint32_t o) { uint32_t r; asm("lop3.b32 %0, %1, %2, %3, 0xe2;" : "=r"(r) : "r"(w), "r"(m), "r"(o)); return r; }
__device__ __forceinline__ uint32_t or3(uint32_t a, uint32_t b, uint32_t c) { uint32_t r; asm("lop3.b32 %0, %1, %2, %3, 0xfe;" : "=r"(r) : "r"(a), "r"(b), "r"(c)); return r; }
__device__ __forceinline__ uint32_t diff2(uint32_t a, uint32_t b, uint32_t tag) { uint32_t r; asm("lop3.b32 %0, %1, %2, %3, 0x7e;" : "=r"(r) : "r"(a), "r"(b), "r"(tag)); return r; }
__device__ __forceinline__ float2 cmul(float2 a, float2 b) { return make_float2(a.x * b.x - a.y * b.y, a.x * b.y + a.y * b.x); }

template<int TB> __device__ __forceinline__ void wgmma_ss_160_0(float (&d)[96], uint32_t al, uint32_t ah, uint32_t bl, uint32_t bh) {
  asm volatile("{\n.reg .b64 da, db;\nmov.b64 da, {%80, %81};\nmov.b64 db, {%82, %83};\n"
    "wgmma.mma_async.sync.aligned.m64n160k16.f32.bf16.bf16 {%0,%1,%2,%3,%4,%5,%6,%7,%8,%9,%10,%11,%12,%13,%14,%15,%16,%17,%18,%19,%20,%21,%22,%23,%24,%25,%26,%27,%28,%29,%30,%31,%32,%33,%34,%35,%36,%37,%38,%39,%40,%41,%42,%43,%44,%45,%46,%47,%48,%49,%50,%51,%52,%53,%54,%55,%56,%57,%58,%59,%60,%61,%62,%63,%64,%65,%66,%67,%68,%69,%70,%71,%72,%73,%74,%75,%76,%77,%78,%79}, da, db, 1, 1, 1, 1, %84;\n}\n"
    : "+f"(d[0]),"+f"(d[1]),"+f"(d[2]),"+f"(d[3]),"+f"(d[4]),"+f"(d[5]),"+f"(d[6]),"+f"(d[7]),"+f"(d[8]),"+f"(d[9]),"+f"(d[10]),"+f"(d[11]),"+f"(d[12]),"+f"(d[13]),"+f"(d[14]),"+f"(d[15]),"+f"(d[16]),"+f"(d[17]),"+f"(d[18]),"+f"(d[19]),"+f"(d[20]),"+f"(d[21]),"+f"(d[22]),"+f"(d[23]),"+f"(d[24]),"+f"(d[25]),"+f"(d[26]),"+f"(d[27]),"+f"(d[28]),"+f"(d[29]),"+f"(d[30]),"+f"(d[31]),"+f"(d[32]),"+f"(d[33]),"+f"(d[34]),"+f"(d[35]),"+f"(d[36]),"+f"(d[37]),"+f"(d[38]),"+f"(d[39]),"+f"(d[40]),"+f"(d[41]),"+f"(d[42]),"+f"(d[43]),"+f"(d[44]),"+f"(d[45]),"+f"(d[46]),"+f"(d[47]),"+f"(d[48]),"+f"(d[49]),"+f"(d[50]),"+f"(d[51]),"+f"(d[52]),"+f"(d[53]),"+f"(d[54]),"+f"(d[55]),"+f"(d[56]),"+f"(d[57]),"+f"(d[58]),"+f"(d[59]),"+f"(d[60]),"+f"(d[61]),"+f"(d[62]),"+f"(d[63]),"+f"(d[64]),"+f"(d[65]),"+f"(d[66]),"+f"(d[67]),"+f"(d[68]),"+f"(d[69]),"+f"(d[70]),"+f"(d[71]),"+f"(d[72]),"+f"(d[73]),"+f"(d[74]),"+f"(d[75]),"+f"(d[76]),"+f"(d[77]),"+f"(d[78]),"+f"(d[79])
    : "r"(al), "r"(ah), "r"(bl), "r"(bh), "n"(TB));
}
template<int TB> __device__ __forceinline__ void wgmma_ss_144_0(float (&d)[96], uint32_t al, uint32_t ah, uint32_t bl, uint32_t bh) {
  asm volatile("{\n.reg .b64 da, db;\nmov.b64 da, {%72, %73};\nmov.b64 db, {%74, %75};\n"
    "wgmma.mma_async.sync.aligned.m64n144k16.f32.bf16.bf16 {%0,%1,%2,%3,%4,%5,%6,%7,%8,%9,%10,%11,%12,%13,%14,%15,%16,%17,%18,%19,%20,%21,%22,%23,%24,%25,%26,%27,%28,%29,%30,%31,%32,%33,%34,%35,%36,%37,%38,%39,%40,%41,%42,%43,%44,%45,%46,%47,%48,%49,%50,%51,%52,%53,%54,%55,%56,%57,%58,%59,%60,%61,%62,%63,%64,%65,%66,%67,%68,%69,%70,%71}, da, db, 1, 1, 1, 1, %76;\n}\n"
    : "+f"(d[0]),"+f"(d[1]),"+f"(d[2]),"+f"(d[3]),"+f"(d[4]),"+f"(d[5]),"+f"(d[6]),"+f"(d[7]),"+f"(d[8]),"+f"(d[9]),"+f"(d[10]),"+f"(d[11]),"+f"(d[12]),"+f"(d[13]),"+f"(d[14]),"+f"(d[15]),"+f"(d[16]),"+f"(d[17]),"+f"(d[18]),"+f"(d[19]),"+f"(d[20]),"+f"(d[21]),"+f"(d[22]),"+f"(d[23]),"+f"(d[24]),"+f"(d[25]),"+f"(d[26]),"+f"(d[27]),"+f"(d[28]),"+f"(d[29]),"+f"(d[30]),"+f"(d[31]),"+f"(d[32]),"+f"(d[33]),"+f"(d[34]),"+f"(d[35]),"+f"(d[36]),"+f"(d[37]),"+f"(d[38]),"+f"(d[39]),"+f"(d[40]),"+f"(d[41]),"+f"(d[42]),"+f"(d[43]),"+f"(d[44]),"+f"(d[45]),"+f"(d[46]),"+f"(d[47]),"+f"(d[48]),"+f"(d[49]),"+f"(d[50]),"+f"(d[51]),"+f"(d[52]),"+f"(d[53]),"+f"(d[54]),"+f"(d[55]),"+f"(d[56]),"+f"(d[57]),"+f"(d[58]),"+f"(d[59]),"+f"(d[60]),"+f"(d[61]),"+f"(d[62]),"+f"(d[63]),"+f"(d[64]),"+f"(d[65]),"+f"(d[66]),"+f"(d[67]),"+f"(d[68]),"+f"(d[69]),"+f"(d[70]),"+f"(d[71])
    : "r"(al), "r"(ah), "r"(bl), "r"(bh), "n"(TB));
}
template<int TB> __device__ __forceinline__ void wgmma_ss_96_0(float (&d)[96], uint32_t al, uint32_t ah, uint32_t bl, uint32_t bh) {
  asm volatile("{\n.reg .b64 da, db;\nmov.b64 da, {%48, %49};\nmov.b64 db, {%50, %51};\n"
    "wgmma.mma_async.sync.aligned.m64n96k16.f32.bf16.bf16 {%0,%1,%2,%3,%4,%5,%6,%7,%8,%9,%10,%11,%12,%13,%14,%15,%16,%17,%18,%19,%20,%21,%22,%23,%24,%25,%26,%27,%28,%29,%30,%31,%32,%33,%34,%35,%36,%37,%38,%39,%40,%41,%42,%43,%44,%45,%46,%47}, da, db, 1, 1, 1, 1, %52;\n}\n"
    : "+f"(d[0]),"+f"(d[1]),"+f"(d[2]),"+f"(d[3]),"+f"(d[4]),"+f"(d[5]),"+f"(d[6]),"+f"(d[7]),"+f"(d[8]),"+f"(d[9]),"+f"(d[10]),"+f"(d[11]),"+f"(d[12]),"+f"(d[13]),"+f"(d[14]),"+f"(d[15]),"+f"(d[16]),"+f"(d[17]),"+f"(d[18]),"+f"(d[19]),"+f"(d[20]),"+f"(d[21]),"+f"(d[22]),"+f"(d[23]),"+f"(d[24]),"+f"(d[25]),"+f"(d[26]),"+f"(d[27]),"+f"(d[28]),"+f"(d[29]),"+f"(d[30]),"+f"(d[31]),"+f"(d[32]),"+f"(d[33]),"+f"(d[34]),"+f"(d[35]),"+f"(d[36]),"+f"(d[37]),"+f"(d[38]),"+f"(d[39]),"+f"(d[40]),"+f"(d[41]),"+f"(d[42]),"+f"(d[43]),"+f"(d[44]),"+f"(d[45]),"+f"(d[46]),"+f"(d[47])
    : "r"(al), "r"(ah), "r"(bl), "r"(bh), "n"(TB));
}
template<int TB> __device__ __forceinline__ void wgmma_ss_96_48(float (&d)[96], uint32_t al, uint32_t ah, uint32_t bl, uint32_t bh) {
  asm volatile("{\n.reg .b64 da, db;\nmov.b64 da, {%48, %49};\nmov.b64 db, {%50, %51};\n"
    "wgmma.mma_async.sync.aligned.m64n96k16.f32.bf16.bf16 {%0,%1,%2,%3,%4,%5,%6,%7,%8,%9,%10,%11,%12,%13,%14,%15,%16,%17,%18,%19,%20,%21,%22,%23,%24,%25,%26,%27,%28,%29,%30,%31,%32,%33,%34,%35,%36,%37,%38,%39,%40,%41,%42,%43,%44,%45,%46,%47}, da, db, 1, 1, 1, 1, %52;\n}\n"
    : "+f"(d[48]),"+f"(d[49]),"+f"(d[50]),"+f"(d[51]),"+f"(d[52]),"+f"(d[53]),"+f"(d[54]),"+f"(d[55]),"+f"(d[56]),"+f"(d[57]),"+f"(d[58]),"+f"(d[59]),"+f"(d[60]),"+f"(d[61]),"+f"(d[62]),"+f"(d[63]),"+f"(d[64]),"+f"(d[65]),"+f"(d[66]),"+f"(d[67]),"+f"(d[68]),"+f"(d[69]),"+f"(d[70]),"+f"(d[71]),"+f"(d[72]),"+f"(d[73]),"+f"(d[74]),"+f"(d[75]),"+f"(d[76]),"+f"(d[77]),"+f"(d[78]),"+f"(d[79]),"+f"(d[80]),"+f"(d[81]),"+f"(d[82]),"+f"(d[83]),"+f"(d[84]),"+f"(d[85]),"+f"(d[86]),"+f"(d[87]),"+f"(d[88]),"+f"(d[89]),"+f"(d[90]),"+f"(d[91]),"+f"(d[92]),"+f"(d[93]),"+f"(d[94]),"+f"(d[95])
    : "r"(al), "r"(ah), "r"(bl), "r"(bh), "n"(TB));
}
__device__ __forceinline__ void wgmma_rs_72(float (&d)[36], uint32_t a0, uint32_t a1, uint32_t a2, uint32_t a3, uint32_t bl, uint32_t bh, int sd) {
  asm volatile("{\n.reg .pred p;\n.reg .b64 db;\nsetp.ne.b32 p, %42, 0;\nmov.b64 db, {%40, %41};\n"
    "wgmma.mma_async.sync.aligned.m64n72k16.f32.bf16.bf16 {%0,%1,%2,%3,%4,%5,%6,%7,%8,%9,%10,%11,%12,%13,%14,%15,%16,%17,%18,%19,%20,%21,%22,%23,%24,%25,%26,%27,%28,%29,%30,%31,%32,%33,%34,%35}, {%36,%37,%38,%39}, db, p, 1, 1, 1;\n}\n"
    : "+f"(d[0]),"+f"(d[1]),"+f"(d[2]),"+f"(d[3]),"+f"(d[4]),"+f"(d[5]),"+f"(d[6]),"+f"(d[7]),"+f"(d[8]),"+f"(d[9]),"+f"(d[10]),"+f"(d[11]),"+f"(d[12]),"+f"(d[13]),"+f"(d[14]),"+f"(d[15]),"+f"(d[16]),"+f"(d[17]),"+f"(d[18]),"+f"(d[19]),"+f"(d[20]),"+f"(d[21]),"+f"(d[22]),"+f"(d[23]),"+f"(d[24]),"+f"(d[25]),"+f"(d[26]),"+f"(d[27]),"+f"(d[28]),"+f"(d[29]),"+f"(d[30]),"+f"(d[31]),"+f"(d[32]),"+f"(d[33]),"+f"(d[34]),"+f"(d[35])
    : "r"(a0), "r"(a1), "r"(a2), "r"(a3), "r"(bl), "r"(bh), "r"(sd));
}
__device__ __forceinline__ void wgmma_rs_48(float (&d)[24], uint32_t a0, uint32_t a1, uint32_t a2, uint32_t a3, uint32_t bl, uint32_t bh, int sd) {
  asm volatile("{\n.reg .pred p;\n.reg .b64 db;\nsetp.ne.b32 p, %30, 0;\nmov.b64 db, {%28, %29};\n"
    "wgmma.mma_async.sync.aligned.m64n48k16.f32.bf16.bf16 {%0,%1,%2,%3,%4,%5,%6,%7,%8,%9,%10,%11,%12,%13,%14,%15,%16,%17,%18,%19,%20,%21,%22,%23}, {%24,%25,%26,%27}, db, p, 1, 1, 1;\n}\n"
    : "+f"(d[0]),"+f"(d[1]),"+f"(d[2]),"+f"(d[3]),"+f"(d[4]),"+f"(d[5]),"+f"(d[6]),"+f"(d[7]),"+f"(d[8]),"+f"(d[9]),"+f"(d[10]),"+f"(d[11]),"+f"(d[12]),"+f"(d[13]),"+f"(d[14]),"+f"(d[15]),"+f"(d[16]),"+f"(d[17]),"+f"(d[18]),"+f"(d[19]),"+f"(d[20]),"+f"(d[21]),"+f"(d[22]),"+f"(d[23])
    : "r"(a0), "r"(a1), "r"(a2), "r"(a3), "r"(bl), "r"(bh), "r"(sd));
}
template<int N,int OFF,int TB> __device__ __forceinline__ void wgmma_ss(float (&d)[96], uint32_t al, uint32_t ah, uint32_t bl, uint32_t bh) {
  if constexpr (N==160 && OFF==0) wgmma_ss_160_0<TB>(d, al, ah, bl, bh);
  else if constexpr (N==144 && OFF==0) wgmma_ss_144_0<TB>(d, al, ah, bl, bh);
  else if constexpr (N==96 && OFF==0) wgmma_ss_96_0<TB>(d, al, ah, bl, bh);
  else if constexpr (N==96 && OFF==48) wgmma_ss_96_48<TB>(d, al, ah, bl, bh);
}

__device__ __forceinline__ void dft3(float2& a, float2& b, float2& c) {
  const float s = 0.86602540378443864676f;
  float2 t = make_float2(b.x + c.x, b.y + c.y), d = make_float2(b.x - c.x, b.y - c.y);
  float2 m = make_float2(fmaf(-0.5f, t.x, a.x), fmaf(-0.5f, t.y, a.y));
  a = make_float2(a.x + t.x, a.y + t.y);
  b = make_float2(fmaf(s, d.y, m.x), fmaf(-s, d.x, m.y));
  c = make_float2(fmaf(-s, d.y, m.x), fmaf(s, d.x, m.y));
}
__device__ __forceinline__ void dft9(float2 (&x)[9]) {
  const float2 w1 = make_float2(0.76604444311897803520f, -0.64278760968653932632f);
  const float2 w2 = make_float2(0.17364817766693034885f, -0.98480775301220805937f);
  const float2 w4 = make_float2(-0.93969262078590838405f, -0.34202014332566873304f);
  dft3(x[0], x[3], x[6]); dft3(x[1], x[4], x[7]); dft3(x[2], x[5], x[8]);
  x[4] = cmul(x[4], w1); x[7] = cmul(x[7], w2); x[5] = cmul(x[5], w2); x[8] = cmul(x[8], w4);
  dft3(x[0], x[1], x[2]); dft3(x[3], x[4], x[5]); dft3(x[6], x[7], x[8]);
  float2 t;
  t = x[1]; x[1] = x[3]; x[3] = t;
  t = x[2]; x[2] = x[6]; x[6] = t;
  t = x[5]; x[5] = x[7]; x[7] = t;
}

__device__ __forceinline__ uint32_t* mod_ptr(Scratch* sc, int u, int t128) {
  const int i = t128 & 15;
  return u < 72 ? sc->moda + (t128 >> 4) * (2 * D_) + 16 * u + 2 * (i & 7) + (i >> 3) : sc->mod + 16 * (u - 72) + i;
}
__device__ __forceinline__ void mod_unit(Scratch* sc, int u, int t128, uint32_t sw_, uint32_t bar, int ph, uint32_t rb, uint32_t tag) {
  const int w = t128 >> 5, l = t128 & 31;
  uint32_t b[18];
#pragma unroll
  for (int i = 0; i < 18; i++) b[i] = lds(red + 512 + (72 * w + 4 * i + (l & 3)) * 4);
  const uint32_t sa = pin(sw_ + (144 * w + (l & 7) + 8 * (l >> 4)) * 32 + (((l >> 3) ^ (l >> 2)) & 1) * 16);
  const uint32_t sr = pin(rb + (l >> 2) * 16 + w * 4);
  uint32_t* const dst = pin(mod_ptr(sc, u, t128));
  const int kind = u / 36;
  const float mul = __uint_as_float(pin(__float_as_uint(kind == 0 ? 16.0f : 1.0f))), add = __uint_as_float(pin(__float_as_uint(kind == 1 || kind == 4 ? 1.0f : 0.0f)));
  mbar_wait(bar, ph);
  if (t128 == 0 && u < 72) TS(10);
  float d[3][4];
#pragma unroll
  for (int i = 0; i < 9; i++) {
    uint32_t a0, a1, a2, a3;
    asm volatile("ldmatrix.sync.aligned.m8n8.x4.trans.shared.b16 {%0,%1,%2,%3}, [%4];" : "=r"(a0), "=r"(a1), "=r"(a2), "=r"(a3) : "r"(sa + i * 512) : "memory");
    if (i < 3) mma16<false>(d[i], a0, a1, a2, a3, b[2 * i], b[2 * i + 1]);
    else mma16<true>(d[i % 3], a0, a1, a2, a3, b[2 * i], b[2 * i + 1]);
  }
  if ((l & 3) == 0) { sts(sr, __float_as_uint(d[0][0] + d[1][0] + d[2][0])); sts(sr + 128, __float_as_uint(d[0][2] + d[1][2] + d[2][2])); }
  bar_sync(4, 128);
  const uint4 v = lds4(rb + (l & 15) * 16);
  const float m = rbf(fmaf(rbf((__uint_as_float(v.x) + __uint_as_float(v.y)) + (__uint_as_float(v.z) + __uint_as_float(v.w))), mul, add));
  if (u < 72 || t128 < 16) *dst = __float_as_uint(m) | tag;
}

__device__ __forceinline__ float rsq(float x) { float r; asm("rsqrt.approx.ftz.f32 %0, %1;" : "=f"(r) : "f"(x)); return r; }
__device__ __forceinline__ void ln_stats2(const float (&a)[18], const float (&b)[18], float sc, float& oa, float& ra, float& ob, float& rb) {
  float v[4] = {0.f, 0.f, 0.f, 0.f}, w[4] = {0.f, 0.f, 0.f, 0.f};
#pragma unroll
  for (int i = 0; i < 18; i += 2) {
    v[0] += a[i]; v[1] = fmaf(a[i], a[i], v[1]); v[2] += b[i]; v[3] = fmaf(b[i], b[i], v[3]);
    w[0] += a[i + 1]; w[1] = fmaf(a[i + 1], a[i + 1], w[1]); w[2] += b[i + 1]; w[3] = fmaf(b[i + 1], b[i + 1], w[3]);
  }
#pragma unroll
  for (int e = 0; e < 4; e++) v[e] += w[e];
#pragma unroll
  for (int o = 16; o; o >>= 1) {
#pragma unroll
    for (int e = 0; e < 4; e++) v[e] += __shfl_xor_sync(0xffffffffu, v[e], o);
  }
  const float ma = v[0] * (1.0f / D_), mb = v[2] * (1.0f / D_);
  ra = sc * rsq(fmaxf(fmaf(-ma, ma, v[1] * (1.0f / D_)), 0.f) + 1e-5f);
  rb = sc * rsq(fmaxf(fmaf(-mb, mb, v[3] * (1.0f / D_)), 0.f) + 1e-5f);
  oa = -ma * ra; ob = -mb * rb;
}

__device__ __forceinline__ float tmat(int c, int q, int j) {
  const int ph = q == 1 ? 1024 * j : (q >> 1) * (c + 128 * j) + 512 * (q & 1);
  return __cosf((float)(((ph + 1024) & 2047) - 1024) * (6.283185307179586f / 2048.0f));
}
__device__ __forceinline__ uint32_t line_off(int k1, int kap, int pi, int f) {
  int kd = 64 * k1 + 9 * kap;
  if (kap == 0 && k1 > 4) kd -= 288;
  if (kd >= D_) kd -= D_;
  return pi * 2400 + ((min(kd, D_ - kd) ^ f) << 3);
}

constexpr int JSK = 5;
struct Ring { uint32_t st, ph; };
template <bool G2, class T> __device__ __forceinline__ void ring_next(T& st, T& ph) {
  if (++st == NST) st = 0;
  ph ^= ((G2 ? 0xDu : 0x1u) >> st) & 1;
}
__device__ __forceinline__ void arrive_if(uint32_t a, uint32_t p) {
  asm volatile("{\n.reg .pred p;\nsetp.ne.u32 p, %1, 0;\n@p mbarrier.arrive.shared::cta.b64 _, [%0];\n}" ::"r"(a), "r"(p) : "memory");
}
template <int NA> __device__ __forceinline__ void reg_fence_n(float (&d)[96]) {
#pragma unroll
  for (int i = 0; i < NA; i++) asm volatile("" : "+f"(d[i])::"memory");
}
template <int MODE>
__device__ __forceinline__ void gemm_main(float (&acc)[96], uint32_t da0, uint32_t da1, uint32_t db0, int wg, Ring& rg,
                                          bool rows, uint32_t* x1p, const uint32_t (&xr)[18]) {
  static_assert(JSK == NST - 1, "the held slot is the first one that is not refilled by GEMM1");
  constexpr int NKB = MODE == 3 ? 36 : 32, J = MODE == 3 ? J2 : JSK;
  constexpr uint32_t HA = 0x40000040u, HB = MODE == 3 ? 0x40000040u : 0x80000020u;
  constexpr uint32_t KA = 2048 >> 4, KB = MODE == 3 ? (32 >> 4) : (1024 >> 4);
  constexpr int NA = MODE == 3 ? 72 : MODE == 1 ? 96 : 80;
  const uint32_t t = threadIdx.x & 127;
  const uint32_t eb = full0 + 8 * NST;
  uint32_t pb = 0, rel = t == 0, prel = 0, ok = 0;
  int n = MODE == 3 ? NKB - J : X1K + 2 * wg;
#pragma unroll 1
  for (int pass = MODE == 3 ? 0 : -1;; pass++) {
#pragma unroll 1
    do {
      const uint32_t so = rg.st * ((MODE == 3 ? STAGE2 : STAGE) >> 4), cb = eb + 8 * rg.st;
      if (__builtin_expect(!ok, 0)) mbar_wait(full0 + 8 * rg.st, rg.ph);
      reg_fence_n<NA>(acc);
      if (MODE == 1 && wg) {
        wg_fence();
#pragma unroll
        for (int k = 0; k < 4; k++) wgmma_ss<96, 48, 1>(acc, da1 + so + k * KA, HA, db0 + so + k * KB, HB);
        wg_commit();
      }
      wg_fence();
#pragma unroll
      for (int k = 0; k < 4; k++) {
        if (k == 3) { ring_next<MODE == 3>(rg.st, rg.ph); ok = PEEK ? mbar_test(full0 + 8 * rg.st, rg.ph) : 0; }
        if (MODE == 0) wgmma_ss<160, 0, 1>(acc, da0 + so + k * KA, HA, db0 + so + k * KB, HB);
        else if (MODE == 3) wgmma_ss<144, 0, 0>(acc, da0 + so + k * KA, HA, db0 + so + k * KB, HB);
        else wgmma_ss<96, 0, 1>(acc, da0 + so + k * KA, HA, db0 + so + k * KB, HB);
      }
      wg_commit();
      wg_wait<1>();
      reg_fence_n<NA>(acc);
      arrive_if(pb, prel);
      pb = cb; prel = rel;
    } while (--n);
    if (pass == 2 - wg) break;
    if (MODE != 3 && pass < 0) {
      if (rows) {
#pragma unroll
        for (int i = 0; i < 9; i++) { x1p[32 * i] = xr[i]; x1p[128 * 288 + 32 * i] = xr[9 + i]; }
      }
      n = NKB - JSK - X1K - 2 * wg;
      continue;
    }
    n = 1;
    if (pass == 0) {
      if (MODE != 3) prel = rel & wg;
      else { rel = 0; if (J < NST) prel = 0; }
      n = J - 1 + wg;
      if (!wg) continue;
      wg_wait<0>();
      arrive_if(pb, prel);
      prel = 0;
    }
    bar_sync(1, 256);
  }
  wg_wait<0>();
  reg_fence_n<NA>(acc);
  if (MODE != 3) arrive_if(pb, MODE == 1 ? prel & ~wg : prel);
}

constexpr float GK1 = 2.0f * 0.7978845608028654f, GK3 = 8.0f * 0.044715f * 0.7978845608028654f;

__device__ __forceinline__ int kb2_order(int i) { const int wv = i / 6; return 6 * (i - 6 * wv) + ((0x431250 >> (4 * wv)) & 7); }

__device__ __forceinline__ int kb2_pos(int kb) { const int hf = kb >= 36, k = kb - 36 * hf, gr = k / 6; return 64 * hf + gr + 6 * ((0x154230 >> (4 * (k - 6 * gr))) & 7); }

__device__ __forceinline__ void wait_flags(const unsigned* p, int idx, unsigned target, uint32_t& ready) {
  int it = 0;
  while (!((ready >> idx) & 1) && it++ < SPIN_MAX) ready = __ballot_sync(0xffffffffu, (int)(ld_rlx(p) - target) >= 0);
}

enum { B_FULL = 0, B_EMPTY = 6, B_S4 = 12, B_S5, B_LAND, B_FLT = B_LAND + 6, B_Z1, B_Z2, B_GO, B_X, B_WM, B_NUM, B_W0 = B_NUM };

__global__ void __launch_bounds__(NTHR, 1)
fused_kernel(const Params p, const __grid_constant__ Maps maps) {
  extern __shared__ __align__(1024) uint8_t smem_raw[];
  const int bx = blockIdx.x, cta = bx < 112 || bx >= 130 ? bx : bx < 114 ? bx + 16 : bx - 2;
  const int tid = threadIdx.x, t128 = tid & 127;
  const int wp = __shfl_sync(0xffffffffu, tid >> 5, 0), wg = wp >> 2;
  const int l = tid & 31, g = l >> 2, t = l & 3;
  Scratch* const sc = p.s;
  const bool rows = cta < 128;
  const int mu = rows ? cta + 4 : cta - 128;
  const int R = mu - 12;

  uint32_t xr[18];
  uint32_t cv[3];
  const unsigned ep0 = ld_rlx(&sc->cnt[C_EP]);
  if (tid == 0) TS(0);
  if (wg == 2) {
#pragma unroll
    for (int i = 0; i < 3; i++) cv[i] = ld_nc(reinterpret_cast<const uint32_t*>(p.c) + min(t128 + 128 * i, 287));
    if (wp == 9 && l < 9 && rows) {
      const int h = 9 * cta + l;
      prefetch_l2(reinterpret_cast<const uint8_t*>(p.wmod) + (size_t)(h >> 1) * (12 * D_) + (h & 1) * (2 * D_), 2 * D_);
    }
    if (tid == 256 && mu < 72) {
      mbar_init(full0 + 8 * B_W0, 1);
      fence_async_smem();
      mbar_expect(full0 + 8 * B_W0, 18432);
#pragma unroll 1
      for (int i = 0; i < 3; i++) tma2d(sbase + O_P2 + i * 6144, &maps.wm, 16 * mu, 192 * i, full0 + 8 * B_W0);
    }
    __syncwarp();
#pragma unroll 1
    for (int u = mu < 72 ? mu : 72 + mu; u < 216; u += u < 72 ? 72 : NCTA) if (u < 72 || t128 < 16) *mod_ptr(sc, u, t128) = 0;
    if (wp == 11 && smem_u32(smem_raw) != sbase) __trap();
    if (wp >= 10 && elect()) {
#pragma unroll 1
      for (int i = wp - 10; i < B_NUM; i += 2) mbar_init(full0 + 8 * i, i == B_FLT ? 4 : i == B_WM ? 3 : i < B_LAND && i != B_S4 ? 2 : 1);
      fence_async_smem();
    }
    __syncwarp();
  } else if (rows) {
    const uint32_t* xs = reinterpret_cast<const uint32_t*>(p.x) + (size_t)(cta + 256 * wp) * 288 + l;
#pragma unroll
    for (int i = 0; i < 9; i++) { xr[i] = ld_nc(xs + 32 * i); xr[9 + i] = ld_nc(xs + 128 * 288 + 32 * i); }
  }
  CK(0);
  if (tid == 64 && cta == NCTA - 1) prefetch_l2(p.tab, sizeof(T_TAB));
  __syncwarp();
  auto tag_of = [](unsigned e) { return (e & 0x7fffu) | 0x8000u; };
  const int kap = 8 * ((wp & 3) ^ (wg & 1)) + g;
  uint32_t tb[4], sb1[3], lo[9];
#pragma unroll
  for (int i = 0; i < 4; i++) tb[i] = pin(pack_bf16(tmat(cta, 8 * (i >> 1) + g, 2 * t + 8 * (i & 1)), tmat(cta, 8 * (i >> 1) + g, 2 * t + 8 * (i & 1) + 1)));
#pragma unroll
  for (int i = 0; i < 3; i++) {
    const int d = 48 * wp + 16 * i + (l & 15);
    sb1[i] = pin(sbase + O_B1 + (l >> 4) * 9216 + (d % 9) * 1024 + (d & 63) * 16);
  }
#pragma unroll
  for (int k1 = 0; k1 < 9; k1++) lo[k1] = pin(sbase + O_Z1 + line_off(k1, kap, 4 * wg + t, cta & 3));
  const uint32_t snt = pin(sbase + O_NRM + ((l & 7) + 8 * (l >> 4)) * 1168 + (48 * wp + (l & 8)) * 2), sn = pin(sbase + O_NRM + wp * 2336 + l * 4);
  const uint32_t smask = pin(t ? 0u : 0xffff0000u);
  const uint32_t* const mp = pin(sc->moda + (cta >> 4) * (2 * D_) + 48 * wp + 2 * g);
  const uint4* const ftab = pin(p.tab + TB_F + (t128 ^ (wg << 5)));

  if (wg == 2) {
#pragma unroll
    for (int i = 0; i < 3; i++) {
      const float c0 = bf_lo(cv[i]), c1 = bf_hi(cv[i]);
      sts(red + 512 + min(t128 + 128 * i, 287) * 4, pack_bf16(__fdividef(c0, 1.0f + __expf(-c0)), __fdividef(c1, 1.0f + __expf(-c1))));
    }
    if (t128 == 0) sts(full0 + 248, ep0 + 1);
    if (wp == 9 && l < 11) asm volatile("prefetch.tensormap [%0];" ::"l"(&maps.z1 + l) : "memory");
    bar_sync(4, 128);
    if (mu < 72) {
      mod_unit(sc, mu, t128, sbase + O_P2, full0 + 8 * B_W0, 0, red, tag_of(upin(ep0) + 1));
      if (t128 == 0) TS(25);
    }
    CK(1);
  }
  const int pi = R / 15, col0 = 20 * (R - 15 * pi);
  const int xu = DF_ * pi + col0, xv = DF_ * (pi ? 16 - pi : 8) + col0;
  auto load_filter = [&](int a) {
    const int x = (a & 1) ? xv : xu;
    const bool wide = (x & 15) > 12;
    mbar_expect(full0 + 8 * B_FLT, wide ? 12288 : 8192);
    tma2d(sbase + O_RAW + a * 12288, &maps.wf[a & 2], x & ~15, 0, full0 + 8 * B_FLT);
    if (wide) tma2d(sbase + O_RAW + a * 12288 + 8192, &maps.wf[(a & 2) + 1], (x & ~15) + 32, 0, full0 + 8 * B_FLT);
  };
  uint4 af[4];
  if (rows) {
    uint2 ms[3], mc[3];
    auto load_mod = [&](uint32_t o = 0) {
#pragma unroll
      for (int i = 0; i < 3; i++) { ms[i] = ld_rlx2(mp + 2 * o + 16 * i); mc[i] = ld_rlx2(mp + 2 * o + D_ + 16 * i); }
    };
    if (wg < 2) {
      float a[18], b[18];
#pragma unroll
      for (int i = 0; i < 9; i++) { a[2 * i] = bf_lo(xr[i]); a[2 * i + 1] = bf_hi(xr[i]); b[2 * i] = bf_lo(xr[9 + i]); b[2 * i + 1] = bf_hi(xr[9 + i]); }
      float oa, ra, ob, rb;
      ln_stats2(a, b, 1.0f, oa, ra, ob, rb);
      CK(1);
      load_mod((__float_as_uint(ra) | __float_as_uint(rb)) >> 31);
#pragma unroll
      for (int i = 0; i < 9; i++) {
        sts(sn + i * 128, pack_bf16(fmaf(a[2 * i], ra, oa), fmaf(a[2 * i + 1], ra, oa)));
        sts(sn + 1168 + i * 128, pack_bf16(fmaf(b[2 * i], rb, ob), fmaf(b[2 * i + 1], rb, ob)));
      }
      CK(2);
      bar_arrive(10, NTHR);
#pragma unroll
      for (int kk = 0; kk < 4; kk++) af[kk] = ld_nc4(ftab + kk * 128);
      bar_sync(1, 256);
      if (tid == 0) TS(2);
    } else {
      bar_sync(10, NTHR);
      load_mod();
      CK(2);
      if (wp >= 10 && elect()) prefetch_l2(reinterpret_cast<const uint8_t*>(wp == 10 ? p.wr : p.wi) + cta * 9248, 9248);
      __syncwarp();
    }
    float rs[3][8];
#pragma unroll
    for (int i = 0; i < 3; i++) {
      uint32_t a0, a1, a2, a3;
      asm volatile("ldmatrix.sync.aligned.m8n8.x4.trans.shared.b16 {%0,%1,%2,%3}, [%4];" : "=r"(a0), "=r"(a1), "=r"(a2), "=r"(a3)
                   : "r"(snt + 32 * i) : "memory");
      mma16<false>(&rs[i][0], a0, a1, a2, a3, tb[0], tb[1]);
      mma16<false>(&rs[i][4], a0, a1, a2, a3, tb[2], tb[3]);
    }
    CK(3);
    const uint32_t tag16 = tag_of(upin(ep0) + 1), tag1 = tag16 & 1;
    {
      int it = 0;
#pragma unroll 1
      while (true) {
        uint32_t bad = 0;
#pragma unroll
        for (int i = 0; i < 3; i++) bad |= diff2(ms[i].x, ms[i].y, tag16) | diff2(mc[i].x, mc[i].y, tag16);
        if (!any(bad & 0xffffu) || ++it > SPIN_MAX) break;
        load_mod();
      }
      CK(4);
      if (tid == 0) TS(3);
#pragma unroll
      for (int i = 0; i < 3; i++) {
        const float c0 = bf_hi(mc[i].x), c1 = bf_hi(mc[i].y);
        const float s0 = __uint_as_float(ms[i].x & smask), s1 = __uint_as_float(ms[i].y & smask);
        stmatrix4(sb1[i], pack_bf16(fmaf(rs[i][0], c0, s0), rs[i][1] * c0), pack_bf16(fmaf(rs[i][2], c1, s1), rs[i][3] * c1),
                  pack_bf16(rs[i][4] * c0, rs[i][5] * c0), pack_bf16(rs[i][6] * c1, rs[i][7] * c1));
      }
    }
    fence_async_smem();
    CK(5);
    if (wg == 2) {
      bar_arrive(5, NTHR);
      if (R >= 0 && elect()) load_filter(wp - 8);
      __syncwarp();
      const int slot = 4 * (cta & 7) + ((cta >> 4) & 3) + 32 * (2 * (cta >> 6) + ((cta >> 3) & 1));
      const uint32_t c0 = upin(40 * slot), c1 = upin(60 * (wp & 1)), src = upin(sbase + O_Z1 + (wp & 1) * 9600);
      const CUtensorMap* mz = upin(&maps.z1);
      unsigned* hint = pin(sc->cnt + C_Z1 + 32 * (wp & 1));
      if (wp < 10) {
        bar_sync(2 + (wp & 1), 160);
        if (elect()) tma_st2d(mz, src, c0, c1);
        pause(HD1);
        if (elect()) red_add(hint, 1);
        bulk_commit_wait();
        if (tid == 256) TS(4);
        __syncwarp();
      }
    } else {
      bar_sync(5, NTHR);
      CK(6);
      float acc[36];
      const uint32_t db = (((sbase + O_B1 + wg * 9216) & 0x3FFFF) >> 4) | ((128 >> 4) << 16);
      wg_fence();
#pragma unroll
      for (int kk = 0; kk < 4; kk++) wgmma_rs_72(acc, af[kk].x, af[kk].y, af[kk].z, af[kk].w, db + kk * 16, 1024 >> 4, kk);
      wg_commit();
      wg_wait<0>();
      reg_fence(acc);
      CK(7);
      float2 za[9], zb[9];
#pragma unroll
      for (int i = 0; i < 9; i++) { za[i] = make_float2(acc[4 * i], acc[4 * i + 2]); zb[i] = make_float2(acc[4 * i + 1], acc[4 * i + 3]); }
      dft9(za); dft9(zb);
      if ((wp & 3) == wg) {
        const float sp = g ? 0.f : 1.f;
#pragma unroll
        for (int k = 1; k < 5; k++) {
          float2 a = za[k], b = za[9 - k];
          za[k] = make_float2(fmaf(sp, b.x, a.x), fmaf(-sp, b.y, a.y)); za[9 - k] = make_float2(fmaf(-sp, a.x, b.x), fmaf(sp, a.y, b.y));
          a = zb[k]; b = zb[9 - k];
          zb[k] = make_float2(fmaf(sp, b.x, a.x), fmaf(-sp, b.y, a.y)); zb[9 - k] = make_float2(fmaf(-sp, a.x, b.x), fmaf(sp, a.y, b.y));
        }
        const uint32_t w0 = set_tag(pack_bf16(za[0].y, 0.f), tag1), w1 = pack_bf16(zb[0].y, 0.f);
        asm volatile("{\n.reg .pred p;\nsetp.eq.u32 p, %3, 0;\n@p st.shared.v2.b32 [%0], {%1,%2};\n}" ::"r"(lo[0] + 288 * 8), "r"(w0), "r"(w1), "r"(g) : "memory");
        za[0].y = g ? za[0].y : 0.f; zb[0].y = g ? zb[0].y : 0.f;
      }
#pragma unroll
      for (int k1 = 0; k1 < 9; k1++) sts2(lo[k1], set_tag(pack_bf16(za[k1].x, za[k1].y), tag1), pack_bf16(zb[k1].x, zb[k1].y));
      fence_async_smem();
      CK(8);
      bar_arrive(2 + wg, 160);
      {
        const uint32_t fx = (((cta >> 4) ^ cta) & 3) << 3, dl = O_IN - O_Z1, st = sbase + O_ST + 15360 + tid * 16;
        sts4(st, (lo[0] ^ fx) + dl, (lo[1] ^ fx) + dl, (lo[2] ^ fx) + dl, (lo[3] ^ fx) + dl);
        sts4(st + 4096, (lo[4] ^ fx) + dl, (lo[5] ^ fx) + dl, (lo[6] ^ fx) + dl, (lo[7] ^ fx) + dl);
        sts4(st + 8192, (lo[8] ^ fx) + dl, (lo[0] ^ fx) + dl + (kap ? 0 : 288 * 8),
             sbase + O_B3 + wg * 1024 + (l >> 4) * 2048 + (2 * (kap & 24) + (l & 15)) * 16, 0);
      }
    }
    {
      uint32_t sy[6];
#pragma unroll
      for (int i = 0; i < 6; i++) {
        const int rr = 16 * (wp & 3) + g + 8 * (i & 1);
        sy[i] = sbase + O_Y + (t * 584 + 64 * ((3 * wg + (i >> 1) + 63 - rr) % 9) + rr) * 4;
      }
      sts4(sbase + O_ST + tid * 16, movm(tb[0]), movm(tb[2]), movm(tb[1]), movm(tb[3]));
      sts4(sbase + O_ST + 6144 + tid * 16, sy[0], sy[1], sy[2], sy[3]);
      sts2(sbase + O_ST + 12288 + tid * 8, sy[4], sy[5]);
    }
  } else {
    __syncthreads();
  }

  const unsigned ep = upin(lds(full0 + 248));
  const uint32_t tag16 = tag_of(ep), tag1 = ep & 1;
  auto load_wm = [&](int u) {
    if (wp > 8 && elect()) {
      mbar_expect(full0 + 8 * B_WM, 6144);
      tma2d(sbase + O_NRM + (wp - 9) * 6144, &maps.wm, 16 * u, 192 * (wp - 9), full0 + 8 * B_WM);
    }
    __syncwarp();
  };
  if (R >= 0) {
    const int nl = (col0 + wp < DF_) + (wg < 2 && col0 + wp + 12 < DF_);
    uint4 cf[2][4], G[4];
#pragma unroll
    for (int i = 0; i < 4; i++) {
      cf[0][i] = __ldg(p.tab + TB_P2 + i * 32 + l);
      cf[1][i] = __ldg(p.tab + TB_P2 + (pi ? i : 4 + i) * 32 + l);
      G[i] = __ldg(p.tab + TB_P2 + (8 + i) * 32 + l);
    }
    const uint32_t* zin = sc->z1 + (size_t)R * 5120;
    if (wp == 10) {
      const uint32_t* zu = upin(zin);
      if (elect()) mbar_expect(full0 + 8 * B_Z1, 20480);
      wait_cnt(sc->cnt + C_Z1 + 32 * (pi >> 2), 128 * ep);
      if (elect()) {
        bulk_ld(sbase + O_P2, zu, 20480, full0 + 8 * B_Z1);
        TS(12);
      }
      __syncwarp();
    }
    mbar_wait(full0 + 8 * B_FLT, 0);
    CK(9);
    float wn[16], wc[16];
#pragma unroll 1
    for (int ln = nl - 1; ln >= 0; ln--) {
      const int col = col0 + wp + 12 * ln, k2 = (57 * col) & 63;
      const bool cj = k2 > 32;
      const float nr = ((col & 31) == 0 && col != 0 && col != 288 ? 0.5f : 1.0f) / ((float)S_ * D_), ni = cj ? -nr : nr;
#pragma unroll
      for (int i = 0; i < 16; i++) wn[i] = wc[i];
#pragma unroll
      for (int cl = 0; cl < 2; cl++) {
        const int v = cl ^ (cj && pi), e = ((v ? xv : xu) & 15) + wp + 12 * ln, sh = e < 32 ? 6 : 5;
        const uint32_t base = sbase + O_RAW + v * 12288 + (e < 32 ? 2 * e : 8192 - 64 + 2 * e), msk = e < 32 ? 0x30 : 0x10;
        const int dm = v ? (cj || pi ? -1 : 0) : 0;
#pragma unroll
        for (int tt = 0; tt < 4; tt++) {
          const int kc = g + 64 * (tt >> 1) + 16 * t + 8 * (tt & 1);
          uint32_t a = base + ((((cj ? -kc : kc) + dm) & 127) << sh);
          a ^= (a >> 3) & msk;
          wc[4 * tt + 2 * cl] = lds_bf(a) * nr; wc[4 * tt + 2 * cl + 1] = lds_bf(a + 24576) * ni;
        }
      }
    }
    const float al = __uint_as_float(pin((pi ? 0x3f800000u : 0u) + (l >> 5)));
    const uint32_t tagv = pin(tag1 + (l >> 5));
    CK(10);
    uint32_t off = pin(l * 160 + ((wp ^ (g & 3)) << 3));
    uint32_t offo = pin(sbase + O_P2 + 20480 + off - 64 * l), po = 3072;
    unsigned* hz2 = pin(sc->cnt + C_Z2);
    const uint32_t do2 = pin(12288 - 32 * l);
    const CUtensorMap* mz2 = upin(&maps.z2[wp == 0]);
    const uint32_t sz2 = upin(sbase + O_P2 + 20480 + (wp ? 0 : 12288)), cz2 = upin(40 * R + (wp ? 0 : 24));
    mbar_wait(full0 + 8 * B_Z1, 0);
    CK(11);
    if (tid == 0) TS(8);
    if (wg == 2) load_wm(72 + mu);
    uint2 v[4], v2[4];
    const uint32_t o2 = nl > 1 ? 96 : 0;
#pragma unroll
    for (int i = 0; i < 4; i++) { v[i] = lds2(sbase + O_P2 + off + i * 5120); v2[i] = lds2(sbase + O_P2 + off + o2 + i * 5120); }
    auto bad2 = [&]() {
      return any(or3(or3(diff2(v[0].x, v[1].x, tagv), diff2(v[2].x, v[3].x, tagv), diff2(v2[0].x, v2[1].x, tagv)), diff2(v2[2].x, v2[3].x, tagv), 0) & 1);
    };
    if (__builtin_expect(bad2() && nl, 0)) {
      FAILCNT(0);
      int it = 0;
      do {
#pragma unroll
        for (int i = 0; i < 4; i++) {
          v[i] = ld_rlx2(reinterpret_cast<const uint8_t*>(zin) + off + i * 5120);
          v2[i] = ld_rlx2(reinterpret_cast<const uint8_t*>(zin) + off + o2 + i * 5120);
        }
      } while (bad2() && ++it < SPIN_MAX);
    }
#pragma unroll 1
    for (int ln = 0; ln < nl; ln++, offo += do2, po = 2048) {
      float d[4][4];
      uint32_t A[8];
#pragma unroll
      for (int h = 0; h < 2; h++) {
        mma16<false>(d[2 * h], cf[0][0].x, cf[0][0].y, cf[0][0].z, cf[0][0].w, v[h].x, v[2 + h].x);
        mma16<false>(d[2 * h + 1], cf[1][0].x, cf[1][0].y, cf[1][0].z, cf[1][0].w, v[h].y, v[2 + h].y);
      }
      if (ln) { fence_async_smem(); bar_arrive(15, NTHR); }
#pragma unroll
      for (int h = 0; h < 2; h++)
#pragma unroll
        for (int L = 0; L < 2; L++) {
          const uint4 tw = cf[L][2 + h];
          const float* z = d[2 * h + L];
          const float2 z0 = cmul(make_float2(z[0], z[2]), make_float2(__uint_as_float(tw.x), __uint_as_float(tw.y)));
          const float2 z1 = cmul(make_float2(z[1], z[3]), make_float2(__uint_as_float(tw.z), __uint_as_float(tw.w)));
          A[4 * h + L] = pack_bf16(z0.x, z0.y); A[4 * h + 2 + L] = pack_bf16(z1.x, z1.y);
        }
#pragma unroll
      for (int tt = 0; tt < 4; tt++) {
        mma16<false>(d[tt], A[0], A[1], A[2], A[3], G[tt].x, G[tt].y);
        mma16<true>(d[tt], A[4], A[5], A[6], A[7], G[tt].z, G[tt].w);
      }
#pragma unroll
      for (int tt = 0; tt < 4; tt++) {
        const float ar = d[tt][0], aj = d[tt][1], br = d[tt][2], bj = d[tt][3];
        const float2 y1 = cmul(make_float2(fmaf(-al, bj, ar), fmaf(al, br, aj)), make_float2(wc[4 * tt], wc[4 * tt + 1]));
        const float2 y2 = cmul(make_float2(fmaf(al, ar, bj), fmaf(al, aj, -br)), make_float2(wc[4 * tt + 2], wc[4 * tt + 3]));
        A[2 * tt] = pack_bf16(fmaf(al, y2.x, y1.x), fmaf(-al, y2.y, -y1.y));
        A[2 * tt + 1] = pack_bf16(fmaf(al, y1.y, -y2.y), fmaf(al, y1.x, -y2.x));
      }
#pragma unroll
      for (int i = 0; i < 16; i++) wc[i] = wn[i];
#pragma unroll
      for (int i = 0; i < 4; i++) v[i] = v2[i];
#pragma unroll
      for (int tt = 0; tt < 4; tt++) {
        mma16<false>(d[tt], A[0], A[1], A[2], A[3], G[tt].x, G[tt].y);
        mma16<true>(d[tt], A[4], A[5], A[6], A[7], G[tt].z, G[tt].w);
      }
#pragma unroll
      for (int h = 0; h < 2; h++)
#pragma unroll
        for (int L = 0; L < 2; L++) {
          const uint4 tw = cf[L][2 + h];
          const float2 z0 = cmul(make_float2(d[2 * h][2 * L], d[2 * h][2 * L + 1]), make_float2(__uint_as_float(tw.x), __uint_as_float(tw.y)));
          const float2 z1 = cmul(make_float2(d[2 * h + 1][2 * L], d[2 * h + 1][2 * L + 1]), make_float2(__uint_as_float(tw.z), __uint_as_float(tw.w)));
          A[4 * h + 2 * L] = movm(pack_bf16(z0.x, z1.x)); A[4 * h + 2 * L + 1] = movm(pack_bf16(z0.y, z1.y));
        }
#pragma unroll
      for (int h = 0; h < 2; h++) {
        mma16<false>(d[0], cf[0][1].x, cf[0][1].y, cf[0][1].z, cf[0][1].w, A[4 * h], A[4 * h + 1]);
        mma16<false>(d[1], cf[1][1].x, cf[1][1].y, cf[1][1].z, cf[1][1].w, A[4 * h + 2], A[4 * h + 3]);
#pragma unroll
        for (int e = 0; e < 2; e++)
          sts2(offo + (2 * h + e) * po, set_tag(pack_bf16(d[0][e], d[0][2 + e]), tagv), pack_bf16(d[1][e], d[1][2 + e]));
      }
      CK(12 + ln);
    }
    if (tid == 0) TS(1);
    fence_async_smem();
    if (nl < 2 && wp != 8) bar_arrive(15, NTHR);
    if (wp & 7) { if (wg < 2) bar_arrive(6, 256); }
    else {
      if (wp) bar_sync(15, NTHR); else bar_sync(6, 256);
      if (elect()) tma_st2d(mz2, sz2, cz2, 0);
      if (wp == 0 && elect()) red_add(hz2, 1);
      if (tid == 0) TS(9);
      if (wp == 0) bulk_commit_wait();
      __syncwarp();
    }
  }
  if (wg == 2) {
#pragma unroll 1
    for (int u = 72 + mu, k = 0; u < 216; u += NCTA, k ^= 1) {
      if (R < 0) { fence_async_smem(); bar_sync(4, 128); load_wm(u); }
      mod_unit(sc, u, t128, sbase + O_NRM, full0 + 8 * B_WM, k, red + 256 - 256 * k, tag16);
    }
    fence_async_smem();
    CK(13);
  }

  const int grp = bx / 11, m1 = bx - 11 * grp;
  const bool helper = (m1 & 3) == 3;
  const int f1 = 384 * grp + (helper ? 192 : 128) * (m1 >> 2);
  const int d1 = 160 * (m1 & 3), flip = m1 >= 7;
  const int a1bytes = helper ? 24576 : 16384;
  auto load_a1 = [&](int st, int kb) {
    mbar_expect(full0 + 8 * st, a1bytes);
    tma4d_ef(sbase + st * STAGE, helper ? &maps.w1b : &maps.w1a, 4 * (kb >> 3), 16 * (kb & 7), f1 >> 6, full0 + 8 * st);
  };

  if (rows) {
#pragma unroll
    for (int kk = 0; kk < 4; kk++) af[kk] = __ldg(p.tab + TB_E + kk * 128 + t128);
    const uint4 c0 = lds4(sbase + O_ST + tid * 16), c1 = lds4(sbase + O_ST + 6144 + tid * 16);
    const uint2 c2 = lds2(sbase + O_ST + 12288 + tid * 8);
    const uint32_t tc[4] = {c0.x, c0.y, c0.z, c0.w}, sy[6] = {c1.x, c1.y, c1.z, c1.w, c2.x, c2.y};
    const uint32_t l8 = pin(8 * l), syl = pin(sbase + O_Y + wp * 2336 + 8 * l);
    uint32_t sh3[3], ham[3];
#pragma unroll
    for (int k = 0; k < 3; k++) {
      const int pos = k && (l >> 4) == k - 1 ? (l & 8) + 4 * (l & 1) + ((l >> 1) & 3) : 4 * (l & 3) + ((l >> 2) & 3);
      const int sw = 2 * cta + (wp & 1), ph = pos ^ ((sw & 3) << 2);
      sh3[k] = pin((wp < 2 ? (l >> 4) * 4096 : sbase + O_B3 + (wp >> 1) * 4608 + (l >> 4) * 256) + (wp & 1) * 128 + ph * 4);
      const bool tg = ((ph ^ sw) & 7) == 0;
      ham[k] = pin(tg ? ~1u : ~0u);
    }
    unsigned* const hh3 = upin(sc->cnt + C_H3 + (cta >> 4));
    uint8_t* const h3g = upin(sc->h3 + (cta >> 4) * (18 * 4096) + (cta & 15) * 256);
    const int slot = 4 * (cta >> 4) + ((cta >> 1) & 3) + 32 * (2 * ((cta >> 3) & 1) + (cta & 1));
    const uint32_t* zin = sc->z2 + (size_t)slot * 4800;
    uint32_t ga[9];
    uint2 sh[9], sw[9];
    auto load_mod3 = [&](int part) {
#pragma unroll
      for (int i = 0; i < 9; i++) {
        if (part != 2) { const uint2 v = lds2(l8 + sbase + O_MOD + 256 * i); ga[i] = __byte_perm(v.x, v.y, 0x7632); }
        if (part != 1) { sh[i] = lds2(l8 + sbase + O_MOD + 4 * D_ + 256 * i); sw[i] = lds2(l8 + sbase + O_MOD + 8 * D_ + 256 * i); }
      }
    };
    if (wg == 2) {
      {
        uint4 v[4];
        const int i3 = min(t128 + 384, 431);
        int it = 0;
        while (true) {
          uint32_t bad = 0;
#pragma unroll
          for (int k = 0; k < 4; k++) v[k] = ld_rlx4(sc->mod + 4 * (k < 3 ? t128 + 128 * k : i3));
#pragma unroll
          for (int k = 0; k < 4; k++) {
            v[k].x ^= tag16; v[k].y ^= tag16; v[k].z ^= tag16; v[k].w ^= tag16;
            bad |= v[k].x | v[k].y | v[k].z | v[k].w;
          }
          if (!any(bad & 0xffffu) || ++it > SPIN_MAX) break;
        }
#pragma unroll
        for (int k = 0; k < 4; k++) sts4(sbase + O_MOD + 16 * (k < 3 ? t128 + 128 * k : i3), v[k].x, v[k].y, v[k].z, v[k].w);
      }
      CK(14);
      bulk_commit_wait();
      bar_sync(10, NTHR);
      mbar_wait(full0 + 8 * B_Z2, 0);
      if (elect()) {
        load_a1(wp - 8, wp - 8);
        if (wp > 8 && wp - 8 < NG1) prefetch_l2(reinterpret_cast<const uint8_t*>(p.w1) + (size_t)(128 * (4 * ((wp - 8) >> 1) + (cta >> 5)) + 64 * (wp & 1) + 2 * (cta & 31)) * (2 * F_), 4 * F_);
      }
      __syncwarp();
    } else {
      const uint4 e0 = lds4(sbase + O_ST + 15360 + tid * 16), e1 = lds4(sbase + O_ST + 19456 + tid * 16), e2 = lds4(sbase + O_ST + 23552 + tid * 16);
      const uint32_t li[9] = {e0.x, e0.y, e0.z, e0.w, e1.x, e1.y, e1.z, e1.w, e2.x}, lx = e2.y, sb3 = e2.z;
      if (MODPOS == 0) bar_arrive(10, NTHR);
      CK(14);
      if (wp == 1) {
        const uint32_t* zu = upin(zin);
        if (elect()) mbar_expect(full0 + 8 * B_Z2, 19200);
        wait_cnt(sc->cnt + C_Z2, 120 * ep);
        if (elect()) {
          bulk_ld(sbase + O_IN, zu, 19200, full0 + 8 * B_Z2);
          TS(14);
        }
        __syncwarp();
      }
      if (MODPOS) { bar_sync(10, NTHR); load_mod3(MODPOS - 1); }
      mbar_wait(full0 + 8 * B_Z2, 0);
      CK(15);
      if (tid == 0) TS(11);
      uint2 v[10];
#pragma unroll
      for (int k1 = 0; k1 < 10; k1++) v[k1] = lds2(k1 < 9 ? li[k1] : lx);
      auto bad3 = [&]() {
        return any(or3(or3(diff2(v[0].x, v[1].x, tag1), diff2(v[2].x, v[3].x, tag1), diff2(v[4].x, v[5].x, tag1)), diff2(v[6].x, v[7].x, tag1), diff2(v[8].x, v[9].x, tag1)) & 1);
      };
      if (__builtin_expect(bad3(), 0)) {
        FAILCNT(1);
        int it = 0;
        do {
#pragma unroll
          for (int k1 = 0; k1 < 10; k1++) v[k1] = ld_rlx2(reinterpret_cast<const uint8_t*>(zin) + ((k1 < 9 ? li[k1] : lx) - (sbase + O_IN)));
        } while (bad3() && ++it < SPIN_MAX);
      }
      float2 za[9], zb[9];
#pragma unroll
      for (int i = 0; i < 9; i++) { za[i] = make_float2(bf_lo(v[i].x), bf_hi(v[i].x)); zb[i] = make_float2(bf_lo(v[i].y), bf_hi(v[i].y)); }
      if ((wp & 3) == wg) {
        const float sp = g ? 0.f : 1.f;
#pragma unroll
        for (int k = 1; k < 5; k++) {
          float2 a = za[k], b = za[9 - k];
          za[k] = make_float2(fmaf(-sp, b.x, a.x), fmaf(sp, b.y, a.y)); za[9 - k] = make_float2(fmaf(sp, a.x, b.x), fmaf(-sp, a.y, b.y));
          a = zb[k]; b = zb[9 - k];
          zb[k] = make_float2(fmaf(-sp, b.x, a.x), fmaf(sp, b.y, a.y)); zb[9 - k] = make_float2(fmaf(sp, a.x, b.x), fmaf(-sp, a.y, b.y));
        }
        za[0].y = g ? za[0].y : bf_lo(v[9].x); zb[0].y = g ? zb[0].y : bf_lo(v[9].y);
      }
      dft9(za); dft9(zb);
#pragma unroll
      for (int n = 0; n < 8; n += 2) {
        const int i0 = (9 - n) % 9, i1 = 8 - n;
        stmatrix4(sb3 + n * 2048, pack_bf16(za[i0].x, zb[i0].x), pack_bf16(za[i0].y, zb[i0].y), pack_bf16(za[i1].x, zb[i1].x), pack_bf16(za[i1].y, zb[i1].y));
      }
      stmatrix2(sb3 + 8 * 2048, pack_bf16(za[1].x, zb[1].x), pack_bf16(za[1].y, zb[1].y));
      fence_async_smem();
    }
    CK(16);
    __syncthreads();
    CK(17);
    float acc[24];
    const uint32_t db = (((sbase + O_B3 + wg * 6144) & 0x3FFFF) >> 4) | ((128 >> 4) << 16);
    wg_fence();
#pragma unroll
    for (int kk = 0; kk < 4; kk++) wgmma_rs_48(acc, af[kk].x, af[kk].y, af[kk].z, af[kk].w, db + kk * 16, 1024 >> 4, kk);
    wg_commit();
    if (wg < 2 && MODPOS == 0) load_mod3(0);
    wg_wait<0>();
    reg_fence(acc);
    CK(18);
#pragma unroll
    for (int i = 0; i < 3; i++) {
      const float* a = &acc[8 * i];
      const uint32_t a0 = pack_bf16(a[0], a[1]), a1 = pack_bf16(a[2], a[3]), a2 = pack_bf16(a[4], a[5]), a3 = pack_bf16(a[6], a[7]);
#pragma unroll
      for (int jh = 0; jh < 2; jh++) {
        float y[4];
        mma16<false>(y, a0, a1, a2, a3, tc[2 * jh], tc[2 * jh + 1]);
        sts(sy[2 * i] + jh * (4 * 584 * 4), pack_bf16(y[0], y[1]));
        sts(sy[2 * i + 1] + jh * (4 * 584 * 4), pack_bf16(y[2], y[3]));
      }
    }
    CK(19);
    if (wg == 2) { bar_arrive(7, NTHR); bar_sync(15, NB15); }
    else {
      bar_sync(7, NTHR);
      if ((LNM >> wp) & 1) bar_sync(15, NB15);
      CK(20);
      float a[18], b[18];
#pragma unroll
      for (int i = 0; i < 9; i++) {
        const uint2 y = lds2(syl + 256 * i);
        xr[i] = hfma2(ga[i], __byte_perm(y.x, y.y, 0x5410), xr[i]);
        xr[9 + i] = hfma2(ga[i], __byte_perm(y.x, y.y, 0x7632), xr[9 + i]);
        a[2 * i] = bf_lo(xr[i]); a[2 * i + 1] = bf_hi(xr[i]); b[2 * i] = bf_lo(xr[9 + i]); b[2 * i + 1] = bf_hi(xr[9 + i]);
      }
      float oa, ra, ob, rb;
      if (MODPOS == 2) load_mod3(2);
      ln_stats2(a, b, 1.0f, oa, ra, ob, rb);
      CK(21);
#pragma unroll
      for (int i = 0; i < 9; i++) {
        const float c0 = __uint_as_float(sw[i].x), c1 = __uint_as_float(sw[i].y), s0 = __uint_as_float(sh[i].x), s1 = __uint_as_float(sh[i].y);
        a[2 * i] = fmaf(fmaf(a[2 * i], ra, oa), c0, s0); a[2 * i + 1] = fmaf(fmaf(a[2 * i + 1], ra, oa), c1, s1);
        b[2 * i] = fmaf(fmaf(b[2 * i], rb, ob), c0, s0); b[2 * i + 1] = fmaf(fmaf(b[2 * i + 1], rb, ob), c1, s1);
      }
      ln_stats2(a, b, 0.5f, oa, ra, ob, rb);
      CK(22);
      if (wp < 2) bar_arrive(15, NB15);
      uint32_t hv[18];
#pragma unroll
      for (int i = 0; i < 9; i++) {
        const int k = i == 2 ? 1 : i == 6 ? 2 : 0;
        hv[2 * i] = bitsel(pack_bf16(fmaf(a[2 * i], ra, oa), fmaf(a[2 * i + 1], ra, oa)), ham[k], tag1);
        hv[2 * i + 1] = bitsel(pack_bf16(fmaf(b[2 * i], rb, ob), fmaf(b[2 * i + 1], rb, ob)), ham[k], tag1);
      }
      if (wp < 2) {
        if (elect()) red_add(hh3, 1);
#pragma unroll
        for (int i = 0; i < 18; i++) {
          const int k = (i >> 1) == 2 ? 1 : (i >> 1) == 6 ? 2 : 0;
          asm volatile("st.global.b32 [%0], %1;" ::"l"(h3g + sh3[k] + (i >> 1) * 8192 + (i & 1) * 64), "r"(hv[i]) : "memory");
        }
        if (tid == 0) TS(13);
      } else {
#pragma unroll
        for (int i = 0; i < 18; i++) sts(sh3[(i >> 1) == 2 ? 1 : (i >> 1) == 6 ? 2 : 0] + (i >> 1) * 512 + (i & 1) * 64, hv[i]);
        fence_async_smem();
      }
      bar_arrive(9, 288);
      CK(23);
    }
  }

  const bool g2 = rows;
  const int z2 = cta, r = z2 >> 6;
  const int s2 = 128 * ((z2 >> 2) & 15), d2 = 144 * (z2 & 3);
  constexpr int ST0 = (32 - JSK - 1) % NST, ST1 = 31 % NST;

  if (wg == 2) {
    asm volatile("setmaxnreg.dec.sync.aligned.u32 40;");
    auto load_b = [&](bool second, int i, int st) {
      const uint32_t lb = full0 + 8 * (B_LAND + st), bytes = second ? 18432 : STAGE - a1bytes;
      mbar_expect(lb, bytes);
      bulk_ld(sbase + (second ? st * STAGE2 + 16384 : st * STAGE + a1bytes),
              second ? sc->u + ((size_t)(36 * r + kb2_order(i)) * D_ + d2) * 128 : sc->h3 + ((size_t)(i * 18 + (d1 >> 5)) << 12), bytes, lb);
    };
    if (wp == 8) {
      int st = rows ? 4 : 0, ph = 1;
#pragma unroll 1
      for (int kb = st; kb < 32; kb++) {
        if (rows && (kb >> 1) == 2) mbar_wait(full0 + 8 * (B_S4 - 4 + kb), 0);
        mbar_wait(empty0 + 8 * st, ph);
        if (elect()) {
          load_a1(st, kb);
          if (kb >= PF2K && kb < PF2K + PF2 && g2)
            prefetch_l2(reinterpret_cast<const uint8_t*>(p.w2) + (size_t)(36 * r + kb2_order(kb - PF2K)) * 262144 + (z2 & 63) * 4096, 4096);
        }
        __syncwarp();
        ring_next<false>(st, ph);
      }
      if (g2) {
        st++;
#pragma unroll 1
        for (int i = 0; i < 36; i++) {
          if (i == HOLDA) mbar_wait(full0 + 8 * B_GO, 0);
          mbar_wait(empty0 + 8 * st, ph);
          if (elect()) {
            mbar_expect(full0 + 8 * st, 16384);
            tma3d_ef(sbase + st * STAGE2, &maps.w2, 64 * (36 * r + kb2_order(i)), s2 >> 6, full0 + 8 * st);
          }
          __syncwarp();
          ring_next<true>(st, ph);
        }
      }
    } else if (wp >= 10) {
      const int sw = wp - 10;
      if (sw) {
        if (rows) {
          bar_sync(9, 288);
          mbar_wait(full0 + 8 * H3W, 0);
          if (elect()) { tma_st3d(&maps.h3, sbase + O_B3 + 4608, 64 * (cta & 15), 18 * (cta >> 4), 1); mbar_arrive(full0 + 8 * B_S4); }
          bulk_commit_wait();
          if (elect()) {
            red_add(sc->cnt + C_H3 + (cta >> 4) + 8, 2);
            mbar_arrive(full0 + 8 * B_S5); mbar_arrive(full0 + 8 * B_S5);
            TS(24);
            asm volatile("fence.acq_rel.gpu;" ::: "memory");
            red_add(&sc->cnt[C_X + 64], 1);
          }
          __syncwarp();
        }
        if (g2) {
          uint2 v[3];
          int it = 0;
          do {
#pragma unroll
            for (int i = 0; i < 3; i++) v[i] = ld_rlx2(sc->mod + 3 * D_ + d2 + 2 * min(l + 32 * i, 71));
          } while (any(or3(diff2(v[0].x, v[0].y, tag16), diff2(v[1].x, v[1].y, tag16), diff2(v[2].x, v[2].y, tag16)) & 0xffffu) && ++it < SPIN_MAX);
#pragma unroll
          for (int i = 0; i < 3; i++) sts(sbase + O_GB + 4 * min(l + 32 * i, 71), __byte_perm(v[i].x, v[i].y, 0x7632));
          __syncwarp();
        }
        wait_cnt<true>(&sc->cnt[C_X + 64], 128 * ep);
        if (elect()) mbar_arrive(full0 + 8 * B_X);
        __syncwarp();
      }
      uint32_t lph = 0;
      auto check_tiles = [&](bool second, int n, int st, uint32_t o1, uint32_t d2nd) {
        const uint32_t b1 = pin(sbase + o1), b2 = pin(sbase + o1 + d2nd);
        int i = 0, it = 0;
#pragma unroll 1
        do {
          const uint32_t so = st * (second ? STAGE2 : STAGE);
          mbar_wait(full0 + 8 * (B_LAND + st), (lph >> st) & 1);
          lph ^= 1u << st;
          uint32_t v[20];
#pragma unroll
          for (int k = 0; k < 20; k++) if (!second || k < 10 || k >= 12) v[k] = lds(k < 12 ? b1 + so + k * 1024 : b2 + so + (k - 12) * 1024); else v[k] = tag1;
#pragma unroll
          for (int k = 0; k < 10; k++) v[k] = diff2(v[2 * k], v[2 * k + 1], tag1);
          const uint32_t bad = or3(or3(or3(v[0], v[1], v[2]), or3(v[3], v[4], v[5]), v[6]), v[7], or3(v[8], v[9], 0));
          if (__builtin_expect(any(bad & 1) && ++it < SPIN_MAX, 0)) {
            FAILCNT(2 + second);
            fence_async_smem();
            __syncwarp();
            if (elect()) load_b(second, i, st);
            __syncwarp();
            continue;
          }
          if (elect()) mbar_arrive(full0 + 8 * st);
          if (++st == NST) st = 0;
          i++;
        } while (i < n);
      };
      if (!sw) check_tiles(false, NV1, 0, a1bytes + l * 32 + (l >> 2) * 4, helper ? 4096 : 12288);
      const bool first = helper || m1 < W0N;
#pragma unroll 1
      for (int k = sw ? first : !first; k <= sw; k++) {
        const uint32_t stg = sbase + (!k ? ST0 * STAGE : helper ? ST1 * STAGE : O_U1);
        const int kbA = (f1 >> 6) + (helper ? 2 : 1) * (k ^ flip), kbB = helper ? (f1 >> 6) + 1 : kbA;
        uint8_t* const uA = upin(sc->u + ((size_t)kbA * D_ + d1) * 128);
        uint8_t* const uB = upin(sc->u + ((size_t)kbB * D_ + (helper ? d1 : d1 + 96)) * 128);
        unsigned* const fA = pin(sc->cnt + C_U + kb2_pos(kbA));
        unsigned* const fB = pin(sc->cnt + C_U + kb2_pos(kbB));
        const bool slow = sw && !helper;
        bar_sync(11 + k, 160);
        if (!slow) { if (elect()) { bulk_st(uA, stg, 96 * 128); TS(k ? 31 : 30); } __syncwarp(); }
        bar_sync(13 + k, 160);
        if (slow) {
          if (g2) mbar_wait(full0 + 8 * B_GO, 0);
          if (first) pause(10 * TRK0);
#pragma unroll 1
          for (int i = 0; i < 20480; i += 2048) {
            if (elect()) bulk_st(uA + i, stg + i, 2048);
            pause(k ? TRKC : TRK0);
          }
        }
        if (elect()) red_add(fA, 1);
        if ((helper ? k : !slow) && elect()) bulk_st(uB, stg + 96 * 128, helper ? 96 * 128 : 64 * 128);
        bulk_commit_wait();
        if (helper && k && elect()) red_add(fB, 1);
        if (elect()) {
          if (!k || helper) mbar_arrive(empty0 + 8 * (k ? ST1 : ST0));
          TS(k ? 23 : 17);
          mbar_arrive(full0 + 8 * B_S5);
        }
        __syncwarp();
      }
      if (sw) {
        mbar_wait(full0 + 8 * B_S5, rows);
        if (elect()) { asm volatile("fence.acq_rel.gpu;" ::: "memory"); red_add(&sc->cnt[C_X], 1); }
        __syncwarp();
      }
      if (g2) {
        if (!sw) check_tiles(true, NV2, 3, 16384 + l * 32 + (4 * (g & 1) + (g >> 1)) * 4, 10240);
        else {
          wait_cnt<true>(&sc->cnt[C_X], NCTA * ep);
          if (elect()) {
            mbar_arrive(full0 + 8 * B_X);
            if (cta == 0) sc->cnt[C_EP] = ep;
          }
          __syncwarp();
        }
      }
      __syncwarp();
    } else {
      uint32_t ready = 0;
      int st = 0, ph = 1;
#pragma unroll 1
      for (int kb = 0; kb < 32; kb++) {
        const uint8_t* src = upin(sc->h3 + ((size_t)(kb * 18 + (d1 >> 5)) << 12));
        const uint32_t dst = upin(sbase + st * STAGE + a1bytes), lb = full0 + 8 * ((kb < NV1 ? B_LAND : 0) + st);
        if (kb == NV1) { mbar_wait(full0 + 8 * B_X, 0); fence_async_glb(); ready = ~0u; }
        if (rows && (kb >> 1) == 2) mbar_wait(full0 + 8 * (B_S4 - 4 + kb), 0);
        mbar_wait(empty0 + 8 * st, ph);
        if (elect()) mbar_expect(lb, STAGE - a1bytes);
        wait_flags(sc->cnt + C_H3 + l, (kb & 7) + (kb < 8 ? 0 : 8), 32 * ep, ready);
        if (elect()) bulk_ld(dst, src, STAGE - a1bytes, lb);
        ring_next<false>(st, ph);
      }
      if (g2) {
        ready = 0;
        st++;
#pragma unroll 1
        for (int i = 0; i < 36; i++) {
          const int kb = kb2_order(i);
          const uint8_t* src = upin(sc->u + ((size_t)(36 * r + kb) * D_ + d2) * 128);
          const uint32_t dst = upin(sbase + st * STAGE2 + 16384), lb = full0 + 8 * ((i < NV2 ? B_LAND : 0) + st);
          if (i == NV2) { mbar_wait(full0 + 8 * B_X, 1); fence_async_glb(); ready = ~0u; }
          mbar_wait(empty0 + 8 * st, ph);
          if (elect()) mbar_expect(lb, 18432);
          wait_flags(sc->cnt + C_U + 64 * r + l, i & 31, 4 * ep, ready);
          if (elect()) {
            bulk_ld(dst, src, 18432, lb);
            if (i == GOAT) mbar_arrive(full0 + 8 * B_GO);
          }
          ring_next<true>(st, ph);
        }
      }
    }
  } else {
    asm volatile("setmaxnreg.inc.sync.aligned.u32 232;");
    const int wgu = wg;
    constexpr uint32_t sb4 = sbase >> 4;
    const int w = wp & 3;
    Ring rg = {0, 0};
    uint32_t* const x1p = p.out + (size_t)(cta + 256 * wp) * 288 + l;
    const uint32_t ad = pin(sbase + (!wg ? ST0 * STAGE : helper ? ST1 * STAGE : O_U1) + (8 * (l >> 4) + (l & 7)) * 128 + (((2 * w + ((l >> 3) & 1)) ^ (l & 7)) << 4));
    const uint32_t uam = pin(g == 2 * t ? 0xfffefffeu : ~0u), uom = tag1 * 0x10001u;
    float acc[96];
    constexpr uint32_t LA = (8192 >> 4) << 16, LB = (4096 >> 4) << 16;
    {
      const int fa = f1 + (helper ? 128 : 64) * (wg ^ flip) + 16 * w + g, fb = helper ? f1 + 64 + 16 * w + g : fa;
      const float a0 = 0.5f * __bfloat162float(p.b1[fa]), a1 = 0.5f * __bfloat162float(p.b1[fa + 8]);
      const float b0 = 0.5f * __bfloat162float(p.b1[fb]), b1 = 0.5f * __bfloat162float(p.b1[fb + 8]);
#pragma unroll
      for (int i = 0; i < 96; i++) acc[i] = i < 48 ? ((i & 2) ? a1 : a0) : ((i & 2) ? b1 : b0);
      reg_fence(acc);
    }
    if (!helper) gemm_main<0>(acc, sb4 + (wgu ^ flip) * 512 + LA, 0, sb4 + 1024 + LB, wgu, rg, rows, x1p, xr);
    else {
      float ac2[96];
#pragma unroll
      for (int i = 0; i < 96; i++) asm volatile("mov.b32 %0, %1;" : "=f"(ac2[i]) : "f"(acc[i]));
      gemm_main<1>(ac2, sb4 + (wgu ^ flip) * 1024 + LA, sb4 + 512 + LA, sb4 + 1536 + LB, wgu, rg, rows, x1p, xr);
#pragma unroll
      for (int i = 0; i < 96; i++) asm volatile("mov.b32 %0, %1;" : "=f"(acc[i]) : "f"(ac2[i]));
    }
    if (t128 == 0) { TS(wg ? 16 : 6); if (wg) TSC(5); }
    {
      float tp[2] = {0.f, 0.f};
#pragma unroll
      for (int j = 0; j < 12; j++) {
        const float* a = &acc[8 * j];
        const float k3 = j < 2 ? GK3 : fmaf(tp[j & 1], 0.0f, GK3);
        float o[8];
#pragma unroll
        for (int e = 0; e < 8; e++) {
          float z = a[e] * fmaf(a[e] * k3, a[e], GK1);
          asm("tanh.approx.f32 %0, %0;" : "+f"(z));
          if (e == GDEP) tp[j & 1] = z;
          o[e] = fmaf(a[e], z, a[e]);
        }
        stmatrix4t(ad + j * 2048, bitsel(pack_bf16(o[0], o[1]), uam, uom), pack_bf16(o[2], o[3]), bitsel(pack_bf16(o[4], o[5]), uam, uom), pack_bf16(o[6], o[7]));
        if (j == 5) {
          fence_async_smem();
          bar_arrive(11 + wgu, 160);
        }
        if ((j == 5 && helper && !wgu) || (j == 9 && !helper)) break;
      }
      fence_async_smem();
      bar_arrive(13 + wgu, 160);
      if (t128 == 0) TS(wg ? 29 : 28);
    }
    if (g2) {
      const int mb = wgu ^ r;
      const int odd = z2 & 1;
      uint4 gq[4];
      uint2 gs;
      {
        float a0 = 0.f, a1 = 0.f;
        if (wgu) { a0 = __bfloat162float(p.b2[s2 + 64 * mb + 16 * w + g]); a1 = __bfloat162float(p.b2[s2 + 64 * mb + 16 * w + 8 + g]); }
#pragma unroll
        for (int i = 0; i < 4; i++) gq[i] = lds4(sbase + O_GB + 32 * odd + 64 * i + 16 * t);
        gs = lds2(sbase + O_GB + (odd ? 0 : 256) + 8 * t);
#pragma unroll
        for (int i = 0; i < 72; i++) acc[i] = (i & 2) ? a1 : a0;
      }
      uint32_t* const ob = p.out + (size_t)(s2 + 64 * mb + 16 * w + g) * 288 + (d2 >> 1);
      uint32_t* const oq = pin(ob + 8 * odd + 4 * t);
      uint32_t* const os = pin(ob + (odd ? 0 : 64) + 2 * t);
      rg.st++;
      gemm_main<3>(acc, sb4 + mb * 512 + LA, 0, sb4 + 1024 + (1 << 16), wgu, rg, rows, x1p, xr);
      if (t128 == 0) { TS(wg ? 20 : 19); if (wg) TSC(22); }
      auto finish = [&](const float* aq, const float* as) {
#pragma unroll
        for (int i = 0; i < 8; i++) {
          const float* a = aq + 16 * (i >> 1) + 2 * (i & 1);
          const uint4 gv = gq[i >> 1];
          red_bf16x8(oq + (i & 1) * 2304 + 16 * (i >> 1), hmul2(gv.x, pack_bf16(a[0], a[1])), hmul2(gv.y, pack_bf16(a[4], a[5])),
                     hmul2(gv.z, pack_bf16(a[8], a[9])), hmul2(gv.w, pack_bf16(a[12], a[13])));
        }
#pragma unroll
        for (int i = 0; i < 2; i++) red_bf16x4(os + i * 2304, hmul2(gs.x, pack_bf16(as[2 * i], as[2 * i + 1])), hmul2(gs.y, pack_bf16(as[2 * i + 4], as[2 * i + 5])));
      };
      if (odd) finish(&acc[8], &acc[0]); else finish(&acc[0], &acc[64]);
      if (t128 == 0) TS(wg ? 7 : 21);
      __syncwarp();
    }
  }
}

typedef CUresult (*EncodeFn)(CUtensorMap*, CUtensorMapDataType, cuuint32_t, void*, const cuuint64_t*, const cuuint64_t*, const cuuint32_t*,
                             const cuuint32_t*, CUtensorMapInterleave, CUtensorMapSwizzle, CUtensorMapL2promotion, CUtensorMapFloatOOBfill);

struct Dim { cuuint64_t n, stride; cuuint32_t box; };
template <int RANK>
void make_map(EncodeFn enc, CUtensorMap* m, bool words, int swz, const void* ptr, const Dim (&d)[RANK]) {
  cuuint64_t gd[RANK], gs[RANK];
  cuuint32_t bx[RANK], es[RANK];
  for (int i = 0; i < RANK; i++) { gd[i] = d[i].n; gs[i] = d[i].stride; bx[i] = d[i].box; es[i] = 1; }
  enc(m, words ? CU_TENSOR_MAP_DATA_TYPE_UINT32 : CU_TENSOR_MAP_DATA_TYPE_BFLOAT16, RANK, const_cast<void*>(ptr), gd, gs + 1, bx, es,
      CU_TENSOR_MAP_INTERLEAVE_NONE, static_cast<CUtensorMapSwizzle>(swz),
      swz == 3 ? CU_TENSOR_MAP_L2_PROMOTION_L2_256B : CU_TENSOR_MAP_L2_PROMOTION_NONE, CU_TENSOR_MAP_FLOAT_OOB_FILL_NONE);
}

}

extern "C" void kernel_launch(void* const* d_in, const int* in_sizes, int n_in, void* d_out, int out_size) {
  (void)in_sizes; (void)n_in; (void)out_size;
  static EncodeFn enc = nullptr;
  static void *sptr = nullptr, *tptr = nullptr;
  if (!enc) {
    void* f = nullptr; cudaDriverEntryPointQueryResult qr;
    cudaGetDriverEntryPoint("cuTensorMapEncodeTiled", &f, cudaEnableDefault, &qr);
    enc = reinterpret_cast<EncodeFn>(f);
    cudaFuncSetAttribute(fused_kernel, cudaFuncAttributeMaxDynamicSharedMemorySize, SMEM_BYTES);
    cudaGetSymbolAddress(&sptr, g_s);
    cudaGetSymbolAddress(&tptr, T_TAB);
  }
  Params p;
  p.x = (const __nv_bfloat16*)d_in[0]; p.wr = (const __nv_bfloat16*)d_in[1]; p.wi = (const __nv_bfloat16*)d_in[2];
  p.b1 = (const __nv_bfloat16*)d_in[5]; p.b2 = (const __nv_bfloat16*)d_in[7];
  p.c = (const __nv_bfloat16*)d_in[8]; p.wmod = (const __nv_bfloat16*)d_in[9];
  p.w1 = (const __nv_bfloat16*)d_in[4]; p.w2 = (const __nv_bfloat16*)d_in[6];
  p.out = static_cast<uint32_t*>(d_out); p.s = static_cast<Scratch*>(sptr); p.tab = static_cast<const uint4*>(tptr);
  Maps maps;
  make_map<4>(enc, &maps.w1a, false, 3, p.w1, {{64, 0, 64}, {16, 128 * 2 * F_, 4}, {128, 2 * F_, 16}, {72, 128, 2}});
  make_map<4>(enc, &maps.w1b, false, 3, p.w1, {{64, 0, 64}, {16, 128 * 2 * F_, 4}, {128, 2 * F_, 16}, {72, 128, 3}});
  make_map<3>(enc, &maps.w2, false, 3, p.w2, {{64, 0, 64}, {F_, 2 * S_, 64}, {32, 128, 2}});
  make_map<2>(enc, &maps.z1, true, 0, p.s->z1, {{5120, 0, 40}, {120, 20480, 60}});
  for (int i = 0; i < 2; i++) make_map<2>(enc, &maps.z2[i], true, 0, p.s->z2, {{4800, 0, i ? 16u : 24u}, {128, 19200, 128}});
  for (int i = 0; i < 4; i++) make_map<2>(enc, &maps.wf[i], false, 2 - (i & 1), (i & 2) ? p.wi : p.wr, {{16 * DF_, 0, (i & 1) ? 16u : 32u}, {128, 32 * DF_, 128}});
  make_map<2>(enc, &maps.wm, false, 1, p.wmod, {{6 * D_, 0, 16}, {D_, 12 * D_, 192}});
  make_map<3>(enc, &maps.h3, true, 0, p.s->h3, {{1024, 0, 64}, {144, 4096, 18}, {4, 144 * 4096, 3}});
  fused_kernel<<<NCTA, NTHR, SMEM_BYTES, cudaStreamPerThread>>>(p, maps);
}
```

```cpp
#include <cuda_runtime.h>
#include <cuda_bf16.h>
#include <cuda.h>
#include <stdint.h>

namespace {

constexpr int S_ = 2048, D_ = 576, DF_ = 289, F_ = 4608;
constexpr int NCTA = 132, NTHR = 384;
constexpr int STAGE = 36864, NST = 6;
constexpr int STAGE2 = 34816, O_U1 = NST * STAGE2, O_GB = O_U1 + 20480, SMEM_BYTES = 232448;
constexpr uint32_t sbase = 1024, red = sbase + NST * STAGE, full0 = sbase + SMEM_BYTES - 256, empty0 = full0 + 8 * NST;
constexpr int O_NRM = 0, O_B1 = 19456, O_Z1 = 38912, O_P2 = 59392, O_ST = 3 * STAGE;
constexpr int O_RAW = 4 * STAGE;
constexpr int O_IN = 4 * STAGE, O_Y = O_IN + 19456, O_B3 = O_IN + 38912, O_MOD = O_IN + 57344;

__device__ __align__(128) const uint32_t T_TAB[5632] = {
0x3f803f80,0xbf803f80,0x3f803f80,0xbf803f80,0x3f803f80,0xbf803f80,0x3f803f80,0xbf803f80,0x3f803f80,0xbf803f80,0x3f803f80,0xbf803f80,
0x3f803f80,0xbf803f80,0x3f803f80,0xbf803f80,0x3f7f3f80,0xbdc90000,0x3f223f35,0xbf46bf35,0x3f753f7b,0xbe95be48,0x3ef13f0e,0xbf62bf55,
0x3f623f6d,0xbef1bec4,0x3e953ec4,0xbf75bf6d,0x3f463f55,0xbf22bf0e,0x3dc93e48,0xbf7fbf7b,0x3f7b3f80,0xbe480000,0xbe480000,0xbf7bbf80,
0x3f553f6d,0xbf0ebec4,0xbf0ebec4,0xbf55bf6d,0x3f0e3f35,0xbf55bf35,0xbf55bf35,0xbf0ebf35,0x3e483ec4,0xbf7bbf6d,0xbf7bbf6d,0xbe48bec4,
0x3f753f80,0xbe950000,0xbf62bf35,0xbef1bf35,0x3f223f55,0xbf46bf0e,0xbf7fbf7b,0x3dc9be48,0x3dc93ec4,0xbf7fbf6d,0xbf46bf6d,0x3f223ec4,
0xbef1be48,0xbf62bf7b,0xbe95bf0e,0x3f753f55,0x3f6d3f80,0xbec40000,0xbf6dbf80,0x3ec40000,0x3ec43f35,0xbf6dbf35,0xbec4bf35,0x3f6d3f35,
0xbec40000,0xbf6dbf80,0x3ec40000,0x3f6d3f80,0xbf6dbf35,0xbec4bf35,0x3f6d3f35,0x3ec43f35,0x3f623f80,0xbef10000,0xbe95bf35,0x3f753f35,
0x3dc93f0e,0xbf7fbf55,0x3f223e48,0x3f463f7b,0xbf46bec4,0xbf22bf6d,0x3f7f3f6d,0xbdc93ec4,0xbf75bf7b,0x3e95be48,0x3ef13f55,0xbf62bf0e,
0x3f553f80,0xbf0e0000,0x3f0e0000,0x3f553f80,0xbe483ec4,0xbf7bbf6d,0x3f7b3f6d,0xbe483ec4,0xbf7bbf35,0xbe48bf35,0x3e483f35,0xbf7bbf35,
0xbf0ebf6d,0x3f553ec4,0xbf55bec4,0xbf0ebf6d,0x3f463f80,0xbf220000,0x3f7f3f35,0x3dc93f35,0xbef13e48,0xbf62bf7b,0x3e953f55,0xbf75bf0e,
0xbf75bf6d,0x3e95bec4,0xbf62bec4,0xbef1bf6d,0x3dc9bf0e,0x3f7f3f55,0xbf22bf7b,0x3f463e48,0x3f353f80,0xbf350000,0x3f353f80,0xbf350000,
0xbf350000,0xbf35bf80,0xbf350000,0xbf35bf80,0xbf35bf80,0x3f350000,0xbf35bf80,0x3f350000,0x3f350000,0x3f353f80,0x3f350000,0x3f353f80,
0x3f223f80,0xbf460000,0xbdc93f35,0xbf7fbf35,0xbf62be48,0xbef1bf7b,0xbf75bf55,0x3e95bf0e,0xbe95bf6d,0x3f753ec4,0x3ef1bec4,0x3f623f6d,
0x3f7f3f0e,0x3dc93f55,0x3f463f7b,0xbf223e48,0x3f0e3f80,0xbf550000,0xbf550000,0xbf0ebf80,0xbf7bbec4,0xbe48bf6d,0xbe48bf6d,0x3f7b3ec4,
0x3e48bf35,0x3f7b3f35,0x3f7b3f35,0xbe483f35,0x3f553f6d,0xbf0e3ec4,0xbf0e3ec4,0xbf55bf6d,0x3ef13f80,0xbf620000,0xbf75bf35,0x3e95bf35,
0xbf7fbf0e,0x3dc9bf55,0x3f46be48,0x3f223f7b,0x3f22bec4,0x3f463f6d,0x3dc93f6d,0xbf7fbec4,0x3e953f7b,0xbf75be48,0xbf62bf55,0x3ef1bf0e,
0x3ec43f80,0xbf6d0000,0xbec4bf80,0x3f6d0000,0xbf6dbf35,0x3ec4bf35,0x3f6d3f35,0xbec43f35,0x3f6d0000,0x3ec43f80,0xbf6d0000,0xbec4bf80,
0xbec43f35,0xbf6dbf35,0x3ec4bf35,0x3f6d3f35,0x3e953f80,0xbf750000,0x3ef1bf35,0x3f623f35,0xbf46bf55,0x3f22bf0e,0x3dc93f7b,0xbf7fbe48,
0x3f7f3ec4,0xbdc93f6d,0xbf22bf6d,0x3f46bec4,0xbf623e48,0xbef1bf7b,0x3f753f0e,0xbe953f55,0x3e483f80,0xbf7b0000,0x3f7b0000,0x3e483f80,
0xbf0ebf6d,0x3f55bec4,0xbf553ec4,0xbf0ebf6d,0x3f553f35,0xbf0e3f35,0x3f0ebf35,0x3f553f35,0xbf7bbec4,0x3e48bf6d,0xbe483f6d,0xbf7bbec4,
0x3dc93f80,0xbf7f0000,0x3f463f35,0xbf223f35,0xbe95bf7b,0x3f75be48,0xbf62bf0e,0x3ef1bf55,0x3ef13f6d,0xbf623ec4,0x3f753ec4,0xbe953f6d,
0xbf22bf55,0x3f46bf0e,0xbf7fbe48,0x3dc9bf7b,0x3f80,0xbf800000,0x3f80,0xbf800000,0xbf80,0x3f800000,0xbf80,0x3f800000,
0x3f80,0xbf800000,0x3f80,0xbf800000,0xbf80,0x3f800000,0xbf80,0x3f800000,0xbdc93f80,0xbf7f0000,0xbf463f35,0xbf22bf35,
0x3e95bf7b,0x3f753e48,0x3f62bf0e,0x3ef13f55,0xbef13f6d,0xbf62bec4,0xbf753ec4,0xbe95bf6d,0x3f22bf55,0x3f463f0e,0x3f7fbe48,0x3dc93f7b,
0xbe483f80,0xbf7b0000,0xbf7b0000,0x3e48bf80,0x3f0ebf6d,0x3f553ec4,0x3f553ec4,0xbf0e3f6d,0xbf553f35,0xbf0ebf35,0xbf0ebf35,0x3f55bf35,
0x3f7bbec4,0x3e483f6d,0x3e483f6d,0xbf7b3ec4,0xbe953f80,0xbf750000,0xbef1bf35,0x3f62bf35,0x3f46bf55,0x3f223f0e,0xbdc93f7b,0xbf7f3e48,
0xbf7f3ec4,0xbdc9bf6d,0x3f22bf6d,0x3f463ec4,0x3f623e48,0xbef13f7b,0xbf753f0e,0xbe95bf55,0xbec43f80,0xbf6d0000,0x3ec4bf80,0x3f6d0000,
0x3f6dbf35,0x3ec43f35,0xbf6d3f35,0xbec4bf35,0xbf6d0000,0x3ec4bf80,0x3f6d0000,0xbec43f80,0x3ec43f35,0xbf6d3f35,0xbec4bf35,0x3f6dbf35,
0xbef13f80,0xbf620000,0x3f75bf35,0x3e953f35,0x3f7fbf0e,0x3dc93f55,0xbf46be48,0x3f22bf7b,0xbf22bec4,0x3f46bf6d,0xbdc93f6d,0xbf7f3ec4,
0xbe953f7b,0xbf753e48,0x3f62bf55,0x3ef13f0e,0xbf0e3f80,0xbf550000,0x3f550000,0xbf0e3f80,0x3f7bbec4,0xbe483f6d,0x3e48bf6d,0x3f7bbec4,
0xbe48bf35,0x3f7bbf35,0xbf7b3f35,0xbe48bf35,0xbf553f6d,0xbf0ebec4,0x3f0e3ec4,0xbf553f6d,0xbf223f80,0xbf460000,0x3dc93f35,0xbf7f3f35,
0x3f62be48,0xbef13f7b,0x3f75bf55,0x3e953f0e,0x3e95bf6d,0x3f75bec4,0xbef1bec4,0x3f62bf6d,0xbf7f3f0e,0x3dc9bf55,0xbf463f7b,0xbf22be48,
0xbf353f80,0xbf350000,0xbf353f80,0xbf350000,0x3f350000,0xbf353f80,0x3f350000,0xbf353f80,0x3f35bf80,0x3f350000,0x3f35bf80,0x3f350000,
0xbf350000,0x3f35bf80,0xbf350000,0x3f35bf80,0xbf463f80,0xbf220000,0xbf7f3f35,0x3dc9bf35,0x3ef13e48,0xbf623f7b,0xbe953f55,0xbf753f0e,
0x3f75bf6d,0x3e953ec4,0x3f62bec4,0xbef13f6d,0xbdc9bf0e,0x3f7fbf55,0x3f22bf7b,0x3f46be48,0xbf553f80,0xbf0e0000,0xbf0e0000,0x3f55bf80,
0x3e483ec4,0xbf7b3f6d,0xbf7b3f6d,0xbe48bec4,0x3f7bbf35,0xbe483f35,0xbe483f35,0xbf7b3f35,0x3f0ebf6d,0x3f55bec4,0x3f55bec4,0xbf0e3f6d,
0xbf623f80,0xbef10000,0x3e95bf35,0x3f75bf35,0xbdc93f0e,0xbf7f3f55,0xbf223e48,0x3f46bf7b,0x3f46bec4,0xbf223f6d,0xbf7f3f6d,0xbdc9bec4,
0x3f75bf7b,0x3e953e48,0xbef13f55,0xbf623f0e,0xbf6d3f80,0xbec40000,0x3f6dbf80,0x3ec40000,0xbec43f35,0xbf6d3f35,0x3ec4bf35,0x3f6dbf35,
0x3ec40000,0xbf6d3f80,0xbec40000,0x3f6dbf80,0x3f6dbf35,0xbec43f35,0xbf6d3f35,0x3ec4bf35,0xbf753f80,0xbe950000,0x3f62bf35,0xbef13f35,
0xbf223f55,0xbf463f0e,0x3f7fbf7b,0x3dc93e48,0xbdc93ec4,0xbf7f3f6d,0x3f46bf6d,0x3f22bec4,0x3ef1be48,0xbf623f7b,0x3e95bf0e,0x3f75bf55,
0xbf7b3f80,0xbe480000,0x3e480000,0xbf7b3f80,0xbf553f6d,0xbf0e3ec4,0x3f0ebec4,0xbf553f6d,0xbf0e3f35,0xbf553f35,0x3f55bf35,0xbf0e3f35,
0xbe483ec4,0xbf7b3f6d,0x3f7bbf6d,0xbe483ec4,0xbf7f3f80,0xbdc90000,0xbf223f35,0xbf463f35,0xbf753f7b,0xbe953e48,0xbef13f0e,0xbf623f55,
0xbf623f6d,0xbef13ec4,0xbe953ec4,0xbf753f6d,0xbf463f55,0xbf223f0e,0xbdc93e48,0xbf7f3f7b,0x3f803f80,0xbf803f80,0x3f803f80,0xbf803f80,
0x3f803f80,0xbf803f80,0x3f803f80,0xbf803f80,0x3f803f80,0xbf803f80,0x3f803f80,0xbf803f80,0x3f803f80,0xbf803f80,0x3f803f80,0xbf803f80,
0xbdc90000,0xbf7fbf80,0xbf46bf35,0xbf22bf35,0xbe95be48,0xbf75bf7b,0xbf62bf55,0xbef1bf0e,0xbef1bec4,0xbf62bf6d,0xbf75bf6d,0xbe95bec4,
0xbf22bf0e,0xbf46bf55,0xbf7fbf7b,0xbdc9be48,0xbf7bbf80,0x3e480000,0x3e480000,0x3f7b3f80,0xbf55bf6d,0x3f0e3ec4,0x3f0e3ec4,0x3f553f6d,
0xbf0ebf35,0x3f553f35,0x3f553f35,0x3f0e3f35,0xbe48bec4,0x3f7b3f6d,0x3f7b3f6d,0x3e483ec4,0x3e950000,0x3f753f80,0x3ef13f35,0xbf62bf35,
0x3f463f0e,0x3f223f55,0xbdc93e48,0xbf7fbf7b,0x3f7f3f6d,0x3dc93ec4,0xbf22bec4,0xbf46bf6d,0x3f623f7b,0xbef1be48,0xbf75bf55,0xbe95bf0e,
0x3f6d3f80,0xbec40000,0xbf6dbf80,0x3ec40000,0x3ec43f35,0xbf6dbf35,0xbec4bf35,0x3f6d3f35,0xbec40000,0xbf6dbf80,0x3ec40000,0x3f6d3f80,
0xbf6dbf35,0xbec4bf35,0x3f6d3f35,0x3ec43f35,0xbef10000,0xbf62bf80,0x3f753f35,0x3e953f35,0xbf7fbf55,0xbdc9bf0e,0x3f463f7b,0xbf22be48,
0xbf22bf6d,0x3f463ec4,0xbdc93ec4,0xbf7fbf6d,0x3e95be48,0x3f753f7b,0xbf62bf0e,0xbef1bf55,0xbf55bf80,0x3f0e0000,0xbf0e0000,0xbf55bf80,
0x3e48bec4,0x3f7b3f6d,0xbf7bbf6d,0x3e48bec4,0x3f7b3f35,0x3e483f35,0xbe48bf35,0x3f7b3f35,0x3f0e3f6d,0xbf55bec4,0x3f553ec4,0x3f0e3f6d,
0x3f220000,0x3f463f80,0xbdc9bf35,0x3f7f3f35,0x3f623f7b,0xbef13e48,0x3f753f0e,0x3e953f55,0xbe953ec4,0xbf75bf6d,0x3ef13f6d,0xbf62bec4,
0xbf7fbf55,0x3dc9bf0e,0xbf46be48,0xbf22bf7b,0x3f353f80,0xbf350000,0x3f353f80,0xbf350000,0xbf350000,0xbf35bf80,0xbf350000,0xbf35bf80,
0xbf35bf80,0x3f350000,0xbf35bf80,0x3f350000,0x3f350000,0x3f353f80,0x3f350000,0x3f353f80,0xbf460000,0xbf22bf80,0xbf7fbf35,0x3dc9bf35,
0xbef1bf7b,0x3f623e48,0x3e95bf0e,0x3f753f55,0x3f753ec4,0x3e953f6d,0x3f623f6d,0xbef13ec4,0x3dc93f55,0xbf7fbf0e,0xbf223e48,0xbf46bf7b,
0xbf0ebf80,0x3f550000,0x3f550000,0x3f0e3f80,0x3f7b3ec4,0x3e483f6d,0x3e483f6d,0xbf7bbec4,0xbe483f35,0xbf7bbf35,0xbf7bbf35,0x3e48bf35,
0xbf55bf6d,0x3f0ebec4,0x3f0ebec4,0x3f553f6d,0x3f620000,0x3ef13f80,0xbe953f35,0xbf75bf35,0xbdc93f55,0xbf7fbf0e,0xbf22bf7b,0x3f46be48,
0xbf46bf6d,0x3f22bec4,0x3f7f3ec4,0x3dc93f6d,0x3f753e48,0x3e953f7b,0xbef13f0e,0xbf62bf55,0x3ec43f80,0xbf6d0000,0xbec4bf80,0x3f6d0000,
0xbf6dbf35,0x3ec4bf35,0x3f6d3f35,0xbec43f35,0x3f6d0000,0x3ec43f80,0xbf6d0000,0xbec4bf80,0xbec43f35,0xbf6dbf35,0x3ec4bf35,0x3f6d3f35,
0xbf750000,0xbe95bf80,0x3f623f35,0xbef13f35,0x3f22bf0e,0x3f463f55,0xbf7fbe48,0xbdc9bf7b,0xbdc93f6d,0xbf7fbec4,0x3f46bec4,0x3f223f6d,
0xbef1bf7b,0x3f62be48,0xbe953f55,0xbf75bf0e,0xbe48bf80,0x3f7b0000,0xbf7b0000,0xbe48bf80,0x3f0e3f6d,0xbf553ec4,0x3f55bec4,0x3f0e3f6d,
0xbf55bf35,0x3f0ebf35,0xbf0e3f35,0xbf55bf35,0x3f7b3ec4,0xbe483f6d,0x3e48bf6d,0x3f7b3ec4,0x3f7f0000,0x3dc93f80,0x3f22bf35,0x3f463f35,
0xbf753e48,0xbe95bf7b,0xbef13f55,0xbf62bf0e,0x3f62bec4,0x3ef13f6d,0x3e95bf6d,0x3f753ec4,0xbf463f0e,0xbf22bf55,0xbdc93f7b,0xbf7fbe48,
0x3f80,0xbf800000,0x3f80,0xbf800000,0xbf80,0x3f800000,0xbf80,0x3f800000,0x3f80,0xbf800000,0x3f80,0xbf800000,
0xbf80,0x3f800000,0xbf80,0x3f800000,0xbf7f0000,0x3dc9bf80,0xbf22bf35,0x3f46bf35,0x3f753e48,0xbe953f7b,0x3ef13f55,0xbf623f0e,
0xbf62bec4,0x3ef1bf6d,0xbe95bf6d,0x3f75bec4,0x3f463f0e,0xbf223f55,0x3dc93f7b,0xbf7f3e48,0x3e48bf80,0x3f7b0000,0x3f7b0000,0xbe483f80,
0xbf0e3f6d,0xbf55bec4,0xbf55bec4,0x3f0ebf6d,0x3f55bf35,0x3f0e3f35,0x3f0e3f35,0xbf553f35,0xbf7b3ec4,0xbe48bf6d,0xbe48bf6d,0x3f7bbec4,
0x3f750000,0xbe953f80,0xbf623f35,0xbef1bf35,0xbf22bf0e,0x3f46bf55,0x3f7fbe48,0xbdc93f7b,0x3dc93f6d,0xbf7f3ec4,0xbf46bec4,0x3f22bf6d,
0x3ef1bf7b,0x3f623e48,0x3e953f55,0xbf753f0e,0xbec43f80,0xbf6d0000,0x3ec4bf80,0x3f6d0000,0x3f6dbf35,0x3ec43f35,0xbf6d3f35,0xbec4bf35,
0xbf6d0000,0x3ec4bf80,0x3f6d0000,0xbec43f80,0x3ec43f35,0xbf6d3f35,0xbec4bf35,0x3f6dbf35,0xbf620000,0x3ef1bf80,0x3e953f35,0xbf753f35,
0x3dc93f55,0xbf7f3f0e,0x3f22bf7b,0x3f463e48,0x3f46bf6d,0x3f223ec4,0xbf7f3ec4,0x3dc9bf6d,0xbf753e48,0x3e95bf7b,0x3ef13f0e,0xbf623f55,
0x3f0ebf80,0x3f550000,0xbf550000,0x3f0ebf80,0xbf7b3ec4,0x3e48bf6d,0xbe483f6d,0xbf7b3ec4,0x3e483f35,0xbf7b3f35,0x3f7bbf35,0x3e483f35,
0x3f55bf6d,0x3f0e3ec4,0xbf0ebec4,0x3f55bf6d,0x3f460000,0xbf223f80,0x3f7fbf35,0x3dc93f35,0x3ef1bf7b,0x3f62be48,0xbe95bf0e,0x3f75bf55,
0xbf753ec4,0x3e95bf6d,0xbf623f6d,0xbef1bec4,0xbdc93f55,0xbf7f3f0e,0x3f223e48,0xbf463f7b,0xbf353f80,0xbf350000,0xbf353f80,0xbf350000,
0x3f350000,0xbf353f80,0x3f350000,0xbf353f80,0x3f35bf80,0x3f350000,0x3f35bf80,0x3f350000,0xbf350000,0x3f35bf80,0xbf350000,0x3f35bf80,
0xbf220000,0x3f46bf80,0x3dc9bf35,0x3f7fbf35,0xbf623f7b,0xbef1be48,0xbf753f0e,0x3e95bf55,0x3e953ec4,0xbf753f6d,0xbef13f6d,0xbf623ec4,
0x3f7fbf55,0x3dc93f0e,0x3f46be48,0xbf223f7b,0x3f55bf80,0x3f0e0000,0x3f0e0000,0xbf553f80,0xbe48bec4,0x3f7bbf6d,0x3f7bbf6d,0x3e483ec4,
0xbf7b3f35,0x3e48bf35,0x3e48bf35,0x3f7bbf35,0xbf0e3f6d,0xbf553ec4,0xbf553ec4,0x3f0ebf6d,0x3ef10000,0xbf623f80,0xbf753f35,0x3e95bf35,
0x3f7fbf55,0xbdc93f0e,0xbf463f7b,0xbf223e48,0x3f22bf6d,0x3f46bec4,0x3dc93ec4,0xbf7f3f6d,0xbe95be48,0x3f75bf7b,0x3f62bf0e,0xbef13f55,
0xbf6d3f80,0xbec40000,0x3f6dbf80,0x3ec40000,0xbec43f35,0xbf6d3f35,0x3ec4bf35,0x3f6dbf35,0x3ec40000,0xbf6d3f80,0xbec40000,0x3f6dbf80,
0x3f6dbf35,0xbec43f35,0xbf6d3f35,0x3ec4bf35,0xbe950000,0x3f75bf80,0xbef13f35,0xbf623f35,0xbf463f0e,0x3f22bf55,0x3dc93e48,0xbf7f3f7b,
0xbf7f3f6d,0x3dc9bec4,0x3f22bec4,0xbf463f6d,0xbf623f7b,0xbef13e48,0x3f75bf55,0xbe953f0e,0x3f7bbf80,0x3e480000,0xbe480000,0x3f7bbf80,
0x3f55bf6d,0x3f0ebec4,0xbf0e3ec4,0x3f55bf6d,0x3f0ebf35,0x3f55bf35,0xbf553f35,0x3f0ebf35,0x3e48bec4,0x3f7bbf6d,0xbf7b3f6d,0x3e48bec4,
0x3dc90000,0xbf7f3f80,0x3f46bf35,0xbf223f35,0x3e95be48,0xbf753f7b,0x3f62bf55,0xbef13f0e,0x3ef1bec4,0xbf623f6d,0x3f75bf6d,0xbe953ec4,
0x3f22bf0e,0xbf463f55,0x3f7fbf7b,0xbdc93e48,0x3f803f80,0xbf803f80,0x3f803f80,0xbf803f80,0x3f803f80,0xbf803f80,0x3f803f80,0xbf803f80,
0x3f803f80,0xbf803f80,0x3f803f80,0xbf803f80,0x3f803f80,0xbf803f80,0x3f803f80,0xbf803f80,0xbf7fbf80,0x3dc90000,0xbf22bf35,0x3f463f35,
0xbf75bf7b,0x3e953e48,0xbef1bf0e,0x3f623f55,0xbf62bf6d,0x3ef13ec4,0xbe95bec4,0x3f753f6d,0xbf46bf55,0x3f223f0e,0xbdc9be48,0x3f7f3f7b,
0x3f7b3f80,0xbe480000,0xbe480000,0xbf7bbf80,0x3f553f6d,0xbf0ebec4,0xbf0ebec4,0xbf55bf6d,0x3f0e3f35,0xbf55bf35,0xbf55bf35,0xbf0ebf35,
0x3e483ec4,0xbf7bbf6d,0xbf7bbf6d,0xbe48bec4,0xbf75bf80,0x3e950000,0x3f623f35,0x3ef13f35,0xbf22bf55,0x3f463f0e,0x3f7f3f7b,0xbdc93e48,
0xbdc9bec4,0x3f7f3f6d,0x3f463f6d,0xbf22bec4,0x3ef13e48,0x3f623f7b,0x3e953f0e,0xbf75bf55,0x3f6d3f80,0xbec40000,0xbf6dbf80,0x3ec40000,
0x3ec43f35,0xbf6dbf35,0xbec4bf35,0x3f6d3f35,0xbec40000,0xbf6dbf80,0x3ec40000,0x3f6d3f80,0xbf6dbf35,0xbec4bf35,0x3f6d3f35,0x3ec43f35,
0xbf62bf80,0x3ef10000,0x3e953f35,0xbf75bf35,0xbdc9bf0e,0x3f7f3f55,0xbf22be48,0xbf46bf7b,0x3f463ec4,0x3f223f6d,0xbf7fbf6d,0x3dc9bec4,
0x3f753f7b,0xbe953e48,0xbef1bf55,0x3f623f0e,0x3f553f80,0xbf0e0000,0x3f0e0000,0x3f553f80,0xbe483ec4,0xbf7bbf6d,0x3f7b3f6d,0xbe483ec4,
0xbf7bbf35,0xbe48bf35,0x3e483f35,0xbf7bbf35,0xbf0ebf6d,0x3f553ec4,0xbf55bec4,0xbf0ebf6d,0xbf46bf80,0x3f220000,0xbf7fbf35,0xbdc9bf35,
0x3ef1be48,0x3f623f7b,0xbe95bf55,0x3f753f0e,0x3f753f6d,0xbe953ec4,0x3f623ec4,0x3ef13f6d,0xbdc93f0e,0xbf7fbf55,0x3f223f7b,0xbf46be48,
0x3f353f80,0xbf350000,0x3f353f80,0xbf350000,0xbf350000,0xbf35bf80,0xbf350000,0xbf35bf80,0xbf35bf80,0x3f350000,0xbf35bf80,0x3f350000,
0x3f350000,0x3f353f80,0x3f350000,0x3f353f80,0xbf22bf80,0x3f460000,0x3dc9bf35,0x3f7f3f35,0x3f623e48,0x3ef13f7b,0x3f753f55,0xbe953f0e,
0x3e953f6d,0xbf75bec4,0xbef13ec4,0xbf62bf6d,0xbf7fbf0e,0xbdc9bf55,0xbf46bf7b,0x3f22be48,0x3f0e3f80,0xbf550000,0xbf550000,0xbf0ebf80,
0xbf7bbec4,0xbe48bf6d,0xbe48bf6d,0x3f7b3ec4,0x3e48bf35,0x3f7b3f35,0x3f7b3f35,0xbe483f35,0x3f553f6d,0xbf0e3ec4,0xbf0e3ec4,0xbf55bf6d,
0xbef1bf80,0x3f620000,0x3f753f35,0xbe953f35,0x3f7f3f0e,0xbdc93f55,0xbf463e48,0xbf22bf7b,0xbf223ec4,0xbf46bf6d,0xbdc9bf6d,0x3f7f3ec4,
0xbe95bf7b,0x3f753e48,0x3f623f55,0xbef13f0e,0x3ec43f80,0xbf6d0000,0xbec4bf80,0x3f6d0000,0xbf6dbf35,0x3ec4bf35,0x3f6d3f35,0xbec43f35,
0x3f6d0000,0x3ec43f80,0xbf6d0000,0xbec4bf80,0xbec43f35,0xbf6dbf35,0x3ec4bf35,0x3f6d3f35,0xbe95bf80,0x3f750000,0xbef13f35,0xbf62bf35,
0x3f463f55,0xbf223f0e,0xbdc9bf7b,0x3f7f3e48,0xbf7fbec4,0x3dc9bf6d,0x3f223f6d,0xbf463ec4,0x3f62be48,0x3ef13f7b,0xbf75bf0e,0x3e95bf55,
0x3e483f80,0xbf7b0000,0x3f7b0000,0x3e483f80,0xbf0ebf6d,0x3f55bec4,0xbf553ec4,0xbf0ebf6d,0x3f553f35,0xbf0e3f35,0x3f0ebf35,0x3f553f35,
0xbf7bbec4,0x3e48bf6d,0xbe483f6d,0xbf7bbec4,0xbdc9bf80,0x3f7f0000,0xbf46bf35,0x3f22bf35,0x3e953f7b,0xbf753e48,0x3f623f0e,0xbef13f55,
0xbef1bf6d,0x3f62bec4,0xbf75bec4,0x3e95bf6d,0x3f223f55,0xbf463f0e,0x3f7f3e48,0xbdc93f7b,0x3f80,0xbf800000,0x3f80,0xbf800000,
0xbf80,0x3f800000,0xbf80,0x3f800000,0x3f80,0xbf800000,0x3f80,0xbf800000,0xbf80,0x3f800000,0xbf80,0x3f800000,
0x3dc9bf80,0x3f7f0000,0x3f46bf35,0x3f223f35,0xbe953f7b,0xbf75be48,0xbf623f0e,0xbef1bf55,0x3ef1bf6d,0x3f623ec4,0x3f75bec4,0x3e953f6d,
0xbf223f55,0xbf46bf0e,0xbf7f3e48,0xbdc9bf7b,0xbe483f80,0xbf7b0000,0xbf7b0000,0x3e48bf80,0x3f0ebf6d,0x3f553ec4,0x3f553ec4,0xbf0e3f6d,
0xbf553f35,0xbf0ebf35,0xbf0ebf35,0x3f55bf35,0x3f7bbec4,0x3e483f6d,0x3e483f6d,0xbf7b3ec4,0x3e95bf80,0x3f750000,0x3ef13f35,0xbf623f35,
0xbf463f55,0xbf22bf0e,0x3dc9bf7b,0x3f7fbe48,0x3f7fbec4,0x3dc93f6d,0xbf223f6d,0xbf46bec4,0xbf62be48,0x3ef1bf7b,0x3f75bf0e,0x3e953f55,
0xbec43f80,0xbf6d0000,0x3ec4bf80,0x3f6d0000,0x3f6dbf35,0x3ec43f35,0xbf6d3f35,0xbec4bf35,0xbf6d0000,0x3ec4bf80,0x3f6d0000,0xbec43f80,
0x3ec43f35,0xbf6d3f35,0xbec4bf35,0x3f6dbf35,0x3ef1bf80,0x3f620000,0xbf753f35,0xbe95bf35,0xbf7f3f0e,0xbdc9bf55,0x3f463e48,0xbf223f7b,
0x3f223ec4,0xbf463f6d,0x3dc9bf6d,0x3f7fbec4,0x3e95bf7b,0x3f75be48,0xbf623f55,0xbef1bf0e,0xbf0e3f80,0xbf550000,0x3f550000,0xbf0e3f80,
0x3f7bbec4,0xbe483f6d,0x3e48bf6d,0x3f7bbec4,0xbe48bf35,0x3f7bbf35,0xbf7b3f35,0xbe48bf35,0xbf553f6d,0xbf0ebec4,0x3f0e3ec4,0xbf553f6d,
0x3f22bf80,0x3f460000,0xbdc9bf35,0x3f7fbf35,0xbf623e48,0x3ef1bf7b,0xbf753f55,0xbe95bf0e,0xbe953f6d,0xbf753ec4,0x3ef13ec4,0xbf623f6d,
0x3f7fbf0e,0xbdc93f55,0x3f46bf7b,0x3f223e48,0xbf353f80,0xbf350000,0xbf353f80,0xbf350000,0x3f350000,0xbf353f80,0x3f350000,0xbf353f80,
0x3f35bf80,0x3f350000,0x3f35bf80,0x3f350000,0xbf350000,0x3f35bf80,0xbf350000,0x3f35bf80,0x3f46bf80,0x3f220000,0x3f7fbf35,0xbdc93f35,
0xbef1be48,0x3f62bf7b,0x3e95bf55,0x3f75bf0e,0xbf753f6d,0xbe95bec4,0xbf623ec4,0x3ef1bf6d,0x3dc93f0e,0xbf7f3f55,0xbf223f7b,0xbf463e48,
0xbf553f80,0xbf0e0000,0xbf0e0000,0x3f55bf80,0x3e483ec4,0xbf7b3f6d,0xbf7b3f6d,0xbe48bec4,0x3f7bbf35,0xbe483f35,0xbe483f35,0xbf7b3f35,
0x3f0ebf6d,0x3f55bec4,0x3f55bec4,0xbf0e3f6d,0x3f62bf80,0x3ef10000,0xbe953f35,0xbf753f35,0x3dc9bf0e,0x3f7fbf55,0x3f22be48,0xbf463f7b,
0xbf463ec4,0x3f22bf6d,0x3f7fbf6d,0x3dc93ec4,0xbf753f7b,0xbe95be48,0x3ef1bf55,0x3f62bf0e,0xbf6d3f80,0xbec40000,0x3f6dbf80,0x3ec40000,
0xbec43f35,0xbf6d3f35,0x3ec4bf35,0x3f6dbf35,0x3ec40000,0xbf6d3f80,0xbec40000,0x3f6dbf80,0x3f6dbf35,0xbec43f35,0xbf6d3f35,0x3ec4bf35,
0x3f75bf80,0x3e950000,0xbf623f35,0x3ef1bf35,0x3f22bf55,0x3f46bf0e,0xbf7f3f7b,0xbdc9be48,0x3dc9bec4,0x3f7fbf6d,0xbf463f6d,0xbf223ec4,
0xbef13e48,0x3f62bf7b,0xbe953f0e,0xbf753f55,0xbf7b3f80,0xbe480000,0x3e480000,0xbf7b3f80,0xbf553f6d,0xbf0e3ec4,0x3f0ebec4,0xbf553f6d,
0xbf0e3f35,0xbf553f35,0x3f55bf35,0xbf0e3f35,0xbe483ec4,0xbf7b3f6d,0x3f7bbf6d,0xbe483ec4,0x3f7fbf80,0x3dc90000,0x3f22bf35,0x3f46bf35,
0x3f75bf7b,0x3e95be48,0x3ef1bf0e,0x3f62bf55,0x3f62bf6d,0x3ef1bec4,0x3e95bec4,0x3f75bf6d,0x3f46bf55,0x3f22bf0e,0x3dc9be48,0x3f7fbf7b,
0x3f803f80,0xbf803f80,0x3f803f80,0xbf803f80,0x3f803f80,0xbf803f80,0x3f803f80,0xbf803f80,0x3f803f80,0xbf803f80,0x3f803f80,0xbf803f80,
0x3f803f80,0xbf803f80,0x3f803f80,0xbf803f80,0x3dc90000,0x3f7f3f80,0x3f463f35,0x3f223f35,0x3e953e48,0x3f753f7b,0x3f623f55,0x3ef13f0e,
0x3ef13ec4,0x3f623f6d,0x3f753f6d,0x3e953ec4,0x3f223f0e,0x3f463f55,0x3f7f3f7b,0x3dc93e48,0xbf7bbf80,0x3e480000,0x3e480000,0x3f7b3f80,
0xbf55bf6d,0x3f0e3ec4,0x3f0e3ec4,0x3f553f6d,0xbf0ebf35,0x3f553f35,0x3f553f35,0x3f0e3f35,0xbe48bec4,0x3f7b3f6d,0x3f7b3f6d,0x3e483ec4,
0xbe950000,0xbf75bf80,0xbef1bf35,0x3f623f35,0xbf46bf0e,0xbf22bf55,0x3dc9be48,0x3f7f3f7b,0xbf7fbf6d,0xbdc9bec4,0x3f223ec4,0x3f463f6d,
0xbf62bf7b,0x3ef13e48,0x3f753f55,0x3e953f0e,0x3f6d3f80,0xbec40000,0xbf6dbf80,0x3ec40000,0x3ec43f35,0xbf6dbf35,0xbec4bf35,0x3f6d3f35,
0xbec40000,0xbf6dbf80,0x3ec40000,0x3f6d3f80,0xbf6dbf35,0xbec4bf35,0x3f6d3f35,0x3ec43f35,0x3ef10000,0x3f623f80,0xbf75bf35,0xbe95bf35,
0x3f7f3f55,0x3dc93f0e,0xbf46bf7b,0x3f223e48,0x3f223f6d,0xbf46bec4,0x3dc9bec4,0x3f7f3f6d,0xbe953e48,0xbf75bf7b,0x3f623f0e,0x3ef13f55,
0xbf55bf80,0x3f0e0000,0xbf0e0000,0xbf55bf80,0x3e48bec4,0x3f7b3f6d,0xbf7bbf6d,0x3e48bec4,0x3f7b3f35,0x3e483f35,0xbe48bf35,0x3f7b3f35,
0x3f0e3f6d,0xbf55bec4,0x3f553ec4,0x3f0e3f6d,0xbf220000,0xbf46bf80,0x3dc93f35,0xbf7fbf35,0xbf62bf7b,0x3ef1be48,0xbf75bf0e,0xbe95bf55,
0x3e95bec4,0x3f753f6d,0xbef1bf6d,0x3f623ec4,0x3f7f3f55,0xbdc93f0e,0x3f463e48,0x3f223f7b,0x3f353f80,0xbf350000,0x3f353f80,0xbf350000,
0xbf350000,0xbf35bf80,0xbf350000,0xbf35bf80,0xbf35bf80,0x3f350000,0xbf35bf80,0x3f350000,0x3f350000,0x3f353f80,0x3f350000,0x3f353f80,
0x3f460000,0x3f223f80,0x3f7f3f35,0xbdc93f35,0x3ef13f7b,0xbf62be48,0xbe953f0e,0xbf75bf55,0xbf75bec4,0xbe95bf6d,0xbf62bf6d,0x3ef1bec4,
0xbdc9bf55,0x3f7f3f0e,0x3f22be48,0x3f463f7b,0xbf0ebf80,0x3f550000,0x3f550000,0x3f0e3f80,0x3f7b3ec4,0x3e483f6d,0x3e483f6d,0xbf7bbec4,
0xbe483f35,0xbf7bbf35,0xbf7bbf35,0x3e48bf35,0xbf55bf6d,0x3f0ebec4,0x3f0ebec4,0x3f553f6d,0xbf620000,0xbef1bf80,0x3e95bf35,0x3f753f35,
0x3dc9bf55,0x3f7f3f0e,0x3f223f7b,0xbf463e48,0x3f463f6d,0xbf223ec4,0xbf7fbec4,0xbdc9bf6d,0xbf75be48,0xbe95bf7b,0x3ef1bf0e,0x3f623f55,
0x3ec43f80,0xbf6d0000,0xbec4bf80,0x3f6d0000,0xbf6dbf35,0x3ec4bf35,0x3f6d3f35,0xbec43f35,0x3f6d0000,0x3ec43f80,0xbf6d0000,0xbec4bf80,
0xbec43f35,0xbf6dbf35,0x3ec4bf35,0x3f6d3f35,0x3f750000,0x3e953f80,0xbf62bf35,0x3ef1bf35,0xbf223f0e,0xbf46bf55,0x3f7f3e48,0x3dc93f7b,
0x3dc9bf6d,0x3f7f3ec4,0xbf463ec4,0xbf22bf6d,0x3ef13f7b,0xbf623e48,0x3e95bf55,0x3f753f0e,0xbe48bf80,0x3f7b0000,0xbf7b0000,0xbe48bf80,
0x3f0e3f6d,0xbf553ec4,0x3f55bec4,0x3f0e3f6d,0xbf55bf35,0x3f0ebf35,0xbf0e3f35,0xbf55bf35,0x3f7b3ec4,0xbe483f6d,0x3e48bf6d,0x3f7b3ec4,
0xbf7f0000,0xbdc9bf80,0xbf223f35,0xbf46bf35,0x3f75be48,0x3e953f7b,0x3ef1bf55,0x3f623f0e,0xbf623ec4,0xbef1bf6d,0xbe953f6d,0xbf75bec4,
0x3f46bf0e,0x3f223f55,0x3dc9bf7b,0x3f7f3e48,0x3f80,0xbf800000,0x3f80,0xbf800000,0xbf80,0x3f800000,0xbf80,0x3f800000,
0x3f80,0xbf800000,0x3f80,0xbf800000,0xbf80,0x3f800000,0xbf80,0x3f800000,0x3f7f0000,0xbdc93f80,0x3f223f35,0xbf463f35,
0xbf75be48,0x3e95bf7b,0xbef1bf55,0x3f62bf0e,0x3f623ec4,0xbef13f6d,0x3e953f6d,0xbf753ec4,0xbf46bf0e,0x3f22bf55,0xbdc9bf7b,0x3f7fbe48,
0x3e48bf80,0x3f7b0000,0x3f7b0000,0xbe483f80,0xbf0e3f6d,0xbf55bec4,0xbf55bec4,0x3f0ebf6d,0x3f55bf35,0x3f0e3f35,0x3f0e3f35,0xbf553f35,
0xbf7b3ec4,0xbe48bf6d,0xbe48bf6d,0x3f7bbec4,0xbf750000,0x3e95bf80,0x3f62bf35,0x3ef13f35,0x3f223f0e,0xbf463f55,0xbf7f3e48,0x3dc9bf7b,
0xbdc9bf6d,0x3f7fbec4,0x3f463ec4,0xbf223f6d,0xbef13f7b,0xbf62be48,0xbe95bf55,0x3f75bf0e,0xbec43f80,0xbf6d0000,0x3ec4bf80,0x3f6d0000,
0x3f6dbf35,0x3ec43f35,0xbf6d3f35,0xbec4bf35,0xbf6d0000,0x3ec4bf80,0x3f6d0000,0xbec43f80,0x3ec43f35,0xbf6d3f35,0xbec4bf35,0x3f6dbf35,
0x3f620000,0xbef13f80,0xbe95bf35,0x3f75bf35,0xbdc9bf55,0x3f7fbf0e,0xbf223f7b,0xbf46be48,0xbf463f6d,0xbf22bec4,0x3f7fbec4,0xbdc93f6d,
0x3f75be48,0xbe953f7b,0xbef1bf0e,0x3f62bf55,0x3f0ebf80,0x3f550000,0xbf550000,0x3f0ebf80,0xbf7b3ec4,0x3e48bf6d,0xbe483f6d,0xbf7b3ec4,
0x3e483f35,0xbf7b3f35,0x3f7bbf35,0x3e483f35,0x3f55bf6d,0x3f0e3ec4,0xbf0ebec4,0x3f55bf6d,0xbf460000,0x3f22bf80,0xbf7f3f35,0xbdc9bf35,
0xbef13f7b,0xbf623e48,0x3e953f0e,0xbf753f55,0x3f75bec4,0xbe953f6d,0x3f62bf6d,0x3ef13ec4,0x3dc9bf55,0x3f7fbf0e,0xbf22be48,0x3f46bf7b,
0xbf353f80,0xbf350000,0xbf353f80,0xbf350000,0x3f350000,0xbf353f80,0x3f350000,0xbf353f80,0x3f35bf80,0x3f350000,0x3f35bf80,0x3f350000,
0xbf350000,0x3f35bf80,0xbf350000,0x3f35bf80,0x3f220000,0xbf463f80,0xbdc93f35,0xbf7f3f35,0x3f62bf7b,0x3ef13e48,0x3f75bf0e,0xbe953f55,
0xbe95bec4,0x3f75bf6d,0x3ef1bf6d,0x3f62bec4,0xbf7f3f55,0xbdc9bf0e,0xbf463e48,0x3f22bf7b,0x3f55bf80,0x3f0e0000,0x3f0e0000,0xbf553f80,
0xbe48bec4,0x3f7bbf6d,0x3f7bbf6d,0x3e483ec4,0xbf7b3f35,0x3e48bf35,0x3e48bf35,0x3f7bbf35,0xbf0e3f6d,0xbf553ec4,0xbf553ec4,0x3f0ebf6d,
0xbef10000,0x3f62bf80,0x3f75bf35,0xbe953f35,0xbf7f3f55,0x3dc9bf0e,0x3f46bf7b,0x3f22be48,0xbf223f6d,0xbf463ec4,0xbdc9bec4,0x3f7fbf6d,
0x3e953e48,0xbf753f7b,0xbf623f0e,0x3ef1bf55,0xbf6d3f80,0xbec40000,0x3f6dbf80,0x3ec40000,0xbec43f35,0xbf6d3f35,0x3ec4bf35,0x3f6dbf35,
0x3ec40000,0xbf6d3f80,0xbec40000,0x3f6dbf80,0x3f6dbf35,0xbec43f35,0xbf6d3f35,0x3ec4bf35,0x3e950000,0xbf753f80,0x3ef1bf35,0x3f62bf35,
0x3f46bf0e,0xbf223f55,0xbdc9be48,0x3f7fbf7b,0x3f7fbf6d,0xbdc93ec4,0xbf223ec4,0x3f46bf6d,0x3f62bf7b,0x3ef1be48,0xbf753f55,0x3e95bf0e,
0x3f7bbf80,0x3e480000,0xbe480000,0x3f7bbf80,0x3f55bf6d,0x3f0ebec4,0xbf0e3ec4,0x3f55bf6d,0x3f0ebf35,0x3f55bf35,0xbf553f35,0x3f0ebf35,
0x3e48bec4,0x3f7bbf6d,0xbf7b3f6d,0x3e48bec4,0xbdc90000,0x3f7fbf80,0xbf463f35,0x3f22bf35,0xbe953e48,0x3f75bf7b,0xbf623f55,0x3ef1bf0e,
0xbef13ec4,0x3f62bf6d,0xbf753f6d,0x3e95bec4,0xbf223f0e,0x3f46bf55,0xbf7f3f7b,0x3dc9be48,0x40003f80,0x3fb53f80,0x3f80,0xbfb53f80,
0x40004000,0xbfb50000,0x0,0xbfb5c000,0x40004000,0xbfb5c000,0x0,0x3fb50000,0x40004000,0x3fb50000,0x0,0x3fb54000,
0x3fff3f80,0x3fa23f80,0xbe49bf80,0xbfc6bf80,0x3ff53ffb,0xbfe2bec8,0xbf15bec8,0xbf71bffb,0x3fe23fed,0xbf15bfed,0xbf71bf44,0x3ff53f44,
0x3fc63fd5,0x3fff3f8e,0xbfa2bf8e,0x3e493fd5,0x3ffb3f80,0x3f8e3f80,0xbec83f80,0xbfd53f80,0x3fd53fed,0xbffbbf44,0xbf8ebf44,0xbec8bfed,
0x3f8e3fb5,0x3ec8bfb5,0xbfd5bfb5,0x3ffb3fb5,0x3ec83f44,0x3fd53fed,0xbffbbfed,0xbf8e3f44,0x3ff53f80,0x3f713f80,0xbf15bf80,0xbfe2bf80,
0x3fa23fd5,0xbfffbf8e,0xbfc6bf8e,0x3e49bfd5,0x3e493f44,0x3fa2bf44,0xbfffbfed,0x3fc63fed,0xbf71bec8,0x3f153ffb,0xbfe2bffb,0xbff5bec8,
0x3fed3f80,0x3f443f80,0xbf443f80,0xbfed3f80,0x3f443fb5,0xbfedbfb5,0xbfedbfb5,0x3f44bfb5,0xbf440000,0x3fed0000,0xbfedc000,0x3f444000,
0xbfedbfb5,0xbf443fb5,0xbf44bfb5,0xbfedbfb5,0x3fe23f80,0x3f153f80,0xbf71bf80,0xbff5bf80,0x3e493f8e,0xbfc6bfd5,0xbfffbfd5,0x3fa2bf8e,
0xbfc6bf44,0x3fff3f44,0xbfa2bfed,0xbe493fed,0xbff5bffb,0xbfe23ec8,0x3f15bec8,0xbf71bffb,0x3fd53f80,0x3ec83f80,0xbf8e3f80,0xbffb3f80,
0xbec83f44,0xbf8ebfed,0xbffbbfed,0x3fd5bf44,0xbffbbfb5,0x3fd53fb5,0xbec8bfb5,0xbf8e3fb5,0xbf8ebfed,0xbffbbf44,0x3fd53f44,0x3ec8bfed,
0x3fc63f80,0x3e493f80,0xbfa2bf80,0xbfffbf80,0xbf713ec8,0xbf15bffb,0xbfe2bffb,0x3ff5bec8,0xbff5bfed,0x3f713fed,0x3f15bf44,0xbfe23f44,
0x3e49bf8e,0xbfa2bfd5,0x3fff3fd5,0x3fc6bf8e,0x3f80,0xbfb53f80,0xc0003f80,0xbfb53f80,0xc000,0x3fb50000,0x40000000,0xbfb54000,
0x4000,0x3fb5c000,0xc0000000,0x3fb50000,0xc000,0xbfb50000,0x40000000,0x3fb5c000,0xbe493f80,0xbfc63f80,0xbfffbf80,0xbfa2bf80,
0x3f15bffb,0x3f713ec8,0x3ff53ec8,0xbfe23ffb,0xbf713fed,0x3ff5bfed,0xbfe2bf44,0x3f153f44,0x3fa2bfd5,0xbe49bf8e,0x3fc63f8e,0x3fffbfd5,
0xbec83f80,0xbfd53f80,0xbffb3f80,0xbf8e3f80,0x3f8ebfed,0x3ec83f44,0x3fd53f44,0xbffb3fed,0xbfd53fb5,0x3ffbbfb5,0xbf8ebfb5,0xbec83fb5,
0x3ffbbf44,0x3f8ebfed,0x3ec83fed,0x3fd5bf44,0xbf153f80,0xbfe23f80,0xbff5bf80,0xbf71bf80,0x3fc6bfd5,0xbe493f8e,0x3fa23f8e,0xbfff3fd5,
0xbfff3f44,0x3fc6bf44,0xbe49bfed,0xbfa23fed,0x3fe23ec8,0x3ff5bffb,0xbf713ffb,0x3f153ec8,0xbf443f80,0xbfed3f80,0xbfed3f80,0xbf443f80,
0x3fedbfb5,0xbf443fb5,0x3f443fb5,0xbfed3fb5,0xbfed0000,0x3f440000,0x3f44c000,0xbfed4000,0x3f443fb5,0x3fedbfb5,0xbfed3fb5,0xbf443fb5,
0xbf713f80,0xbff53f80,0xbfe2bf80,0xbf15bf80,0x3fffbf8e,0xbfa23fd5,0x3e493fd5,0xbfc63f8e,0xbfa2bf44,0xbe493f44,0x3fc6bfed,0xbfff3fed,
0xbf153ffb,0x3f71bec8,0xbff53ec8,0xbfe23ffb,0xbf8e3f80,0xbffb3f80,0xbfd53f80,0xbec83f80,0x3ffbbf44,0xbfd53fed,0xbec83fed,0xbf8e3f44,
0xbec8bfb5,0xbf8e3fb5,0x3ffbbfb5,0xbfd53fb5,0xbfd53fed,0xbec83f44,0xbf8ebf44,0xbffb3fed,0xbfa23f80,0xbfff3f80,0xbfc6bf80,0xbe49bf80,
0x3fe2bec8,0xbff53ffb,0xbf713ffb,0xbf153ec8,0x3f15bfed,0xbfe23fed,0x3ff5bf44,0xbf713f44,0xbfff3f8e,0xbfc63fd5,0x3e49bfd5,0xbfa23f8e,
0xc0003f80,0xbfb53f80,0x3f80,0x3fb53f80,0xc0004000,0x3fb50000,0x0,0x3fb5c000,0xc0004000,0x3fb5c000,0x0,0xbfb50000,
0xc0004000,0xbfb50000,0x0,0xbfb54000,0xbfff3f80,0xbfa23f80,0x3e49bf80,0x3fc6bf80,0xbff53ffb,0x3fe2bec8,0x3f15bec8,0x3f71bffb,
0xbfe23fed,0x3f15bfed,0x3f71bf44,0xbff53f44,0xbfc63fd5,0xbfff3f8e,0x3fa2bf8e,0xbe493fd5,0xbffb3f80,0xbf8e3f80,0x3ec83f80,0x3fd53f80,
0xbfd53fed,0x3ffbbf44,0x3f8ebf44,0x3ec8bfed,0xbf8e3fb5,0xbec8bfb5,0x3fd5bfb5,0xbffb3fb5,0xbec83f44,0xbfd53fed,0x3ffbbfed,0x3f8e3f44,
0xbff53f80,0xbf713f80,0x3f15bf80,0x3fe2bf80,0xbfa23fd5,0x3fffbf8e,0x3fc6bf8e,0xbe49bfd5,0xbe493f44,0xbfa2bf44,0x3fffbfed,0xbfc63fed,
0x3f71bec8,0xbf153ffb,0x3fe2bffb,0x3ff5bec8,0xbfed3f80,0xbf443f80,0x3f443f80,0x3fed3f80,0xbf443fb5,0x3fedbfb5,0x3fedbfb5,0xbf44bfb5,
0x3f440000,0xbfed0000,0x3fedc000,0xbf444000,0x3fedbfb5,0x3f443fb5,0x3f44bfb5,0x3fedbfb5,0xbfe23f80,0xbf153f80,0x3f71bf80,0x3ff5bf80,
0xbe493f8e,0x3fc6bfd5,0x3fffbfd5,0xbfa2bf8e,0x3fc6bf44,0xbfff3f44,0x3fa2bfed,0x3e493fed,0x3ff5bffb,0x3fe23ec8,0xbf15bec8,0x3f71bffb,
0xbfd53f80,0xbec83f80,0x3f8e3f80,0x3ffb3f80,0x3ec83f44,0x3f8ebfed,0x3ffbbfed,0xbfd5bf44,0x3ffbbfb5,0xbfd53fb5,0x3ec8bfb5,0x3f8e3fb5,
0x3f8ebfed,0x3ffbbf44,0xbfd53f44,0xbec8bfed,0xbfc63f80,0xbe493f80,0x3fa2bf80,0x3fffbf80,0x3f713ec8,0x3f15bffb,0x3fe2bffb,0xbff5bec8,
0x3ff5bfed,0xbf713fed,0xbf15bf44,0x3fe23f44,0xbe49bf8e,0x3fa2bfd5,0xbfff3fd5,0xbfc6bf8e,0x3f80,0x3fb53f80,0x40003f80,0x3fb53f80,
0xc000,0xbfb50000,0xc0000000,0x3fb54000,0x4000,0xbfb5c000,0x40000000,0xbfb50000,0xc000,0x3fb50000,0xc0000000,0xbfb5c000,
0x3e493f80,0x3fc63f80,0x3fffbf80,0x3fa2bf80,0xbf15bffb,0xbf713ec8,0xbff53ec8,0x3fe23ffb,0x3f713fed,0xbff5bfed,0x3fe2bf44,0xbf153f44,
0xbfa2bfd5,0x3e49bf8e,0xbfc63f8e,0xbfffbfd5,0x3ec83f80,0x3fd53f80,0x3ffb3f80,0x3f8e3f80,0xbf8ebfed,0xbec83f44,0xbfd53f44,0x3ffb3fed,
0x3fd53fb5,0xbffbbfb5,0x3f8ebfb5,0x3ec83fb5,0xbffbbf44,0xbf8ebfed,0xbec83fed,0xbfd5bf44,0x3f153f80,0x3fe23f80,0x3ff5bf80,0x3f71bf80,
0xbfc6bfd5,0x3e493f8e,0xbfa23f8e,0x3fff3fd5,0x3fff3f44,0xbfc6bf44,0x3e49bfed,0x3fa23fed,0xbfe23ec8,0xbff5bffb,0x3f713ffb,0xbf153ec8,
0x3f443f80,0x3fed3f80,0x3fed3f80,0x3f443f80,0xbfedbfb5,0x3f443fb5,0xbf443fb5,0x3fed3fb5,0x3fed0000,0xbf440000,0xbf44c000,0x3fed4000,
0xbf443fb5,0xbfedbfb5,0x3fed3fb5,0x3f443fb5,0x3f713f80,0x3ff53f80,0x3fe2bf80,0x3f15bf80,0xbfffbf8e,0x3fa23fd5,0xbe493fd5,0x3fc63f8e,
0x3fa2bf44,0x3e493f44,0xbfc6bfed,0x3fff3fed,0x3f153ffb,0xbf71bec8,0x3ff53ec8,0x3fe23ffb,0x3f8e3f80,0x3ffb3f80,0x3fd53f80,0x3ec83f80,
0xbffbbf44,0x3fd53fed,0x3ec83fed,0x3f8e3f44,0x3ec8bfb5,0x3f8e3fb5,0xbffbbfb5,0x3fd53fb5,0x3fd53fed,0x3ec83f44,0x3f8ebf44,0x3ffb3fed,
0x3fa23f80,0x3fff3f80,0x3fc6bf80,0x3e49bf80,0xbfe2bec8,0x3ff53ffb,0x3f713ffb,0x3f153ec8,0xbf15bfed,0x3fe23fed,0xbff5bf44,0x3f713f44,
0x3fff3f8e,0x3fc63fd5,0xbe49bfd5,0x3fa23f8e,0x40004000,0x3fb54000,0x0,0xbfb50000,0x40004000,0xbfb50000,0x0,0xbfb5c000,
0x40004000,0xbfb5c000,0x0,0x3fb50000,0x40004000,0x3fb50000,0x0,0x3fb54000,0x3fa23fb5,0xbe493fb5,0xbfc6bfb5,0xbfffbfb5,
0x3f713f8e,0xbff5bfd5,0xbfe2bfd5,0x3f15bf8e,0x3f153f44,0x3f71bf44,0xbff5bfed,0x3fe23fed,0x3e493ec8,0x3fc63ffb,0xbfffbffb,0xbfa23ec8,
0xbec80000,0xbfd50000,0xbffbc000,0xbf8ec000,0xbf8ebf44,0xbec8bfed,0xbfd5bfed,0x3ffb3f44,0xbfd5bfb5,0x3ffb3fb5,0xbf8ebfb5,0xbec83fb5,
0xbffbbfed,0xbf8e3f44,0xbec8bf44,0xbfd5bfed,0xbfe2bfb5,0xbff5bfb5,0xbf71bfb5,0x3f15bfb5,0xbfffbffb,0x3fc6bec8,0x3e49bec8,0x3fa23ffb,
0xbfc6bfed,0x3e493fed,0x3fa23f44,0xbfffbf44,0xbf15bf8e,0xbfe2bfd5,0x3ff53fd5,0x3f71bf8e,0xbfedc000,0xbf44c000,0x3f440000,0x3fed0000,
0xbf44bfb5,0x3fed3fb5,0x3fed3fb5,0xbf443fb5,0x3f440000,0xbfed0000,0x3fed4000,0xbf44c000,0x3fed3fb5,0x3f44bfb5,0x3f443fb5,0x3fed3fb5,
0xbf15bfb5,0x3f71bfb5,0x3ff53fb5,0x3fe23fb5,0x3fa23ec8,0x3e493ffb,0x3fc63ffb,0xbfffbec8,0x3fff3fed,0xbfa2bfed,0xbe493f44,0x3fc6bf44,
0x3f713fd5,0x3ff53f8e,0xbfe2bf8e,0xbf153fd5,0x3f8e0000,0x3ffb0000,0x3fd54000,0x3ec84000,0x3ffb3fed,0xbfd53f44,0xbec83f44,0xbf8ebfed,
0x3ec83fb5,0x3f8ebfb5,0xbffbbfb5,0x3fd53fb5,0xbfd5bf44,0xbec83fed,0xbf8ebfed,0xbffbbf44,0x3fff3fb5,0x3fc63fb5,0x3e493fb5,0xbfa23fb5,
0x3f153fd5,0xbfe2bf8e,0xbff5bf8e,0x3f71bfd5,0xbfe2bf44,0x3ff53f44,0xbf71bfed,0xbf153fed,0xbfa2bffb,0xbfffbec8,0x3fc63ec8,0x3e49bffb,
0x4000,0xbfb54000,0xc0000000,0xbfb50000,0xc000,0x3fb50000,0x40000000,0xbfb54000,0x4000,0x3fb5c000,0xc0000000,0x3fb50000,
0xc000,0xbfb50000,0x40000000,0x3fb5c000,0xbfc63fb5,0xbfff3fb5,0xbfa2bfb5,0x3e49bfb5,0x3fe2bf8e,0xbf153fd5,0x3f713fd5,0xbff53f8e,
0xbff53f44,0x3fe2bf44,0xbf15bfed,0xbf713fed,0x3fffbec8,0x3fa2bffb,0x3e493ffb,0x3fc6bec8,0xbffb0000,0xbf8e0000,0x3ec8c000,0x3fd5c000,
0x3fd53f44,0xbffb3fed,0xbf8e3fed,0xbec8bf44,0xbf8ebfb5,0xbec83fb5,0x3fd5bfb5,0xbffb3fb5,0x3ec83fed,0x3fd5bf44,0xbffb3f44,0xbf8e3fed,
0xbf71bfb5,0x3f15bfb5,0x3fe2bfb5,0x3ff5bfb5,0xbe493ffb,0xbfa23ec8,0xbfff3ec8,0x3fc6bffb,0x3fa2bfed,0xbfff3fed,0x3fc63f44,0xbe49bf44,
0xbff53f8e,0xbf713fd5,0xbf15bfd5,0xbfe23f8e,0x3f44c000,0x3fedc000,0x3fed0000,0x3f440000,0xbfed3fb5,0x3f44bfb5,0xbf44bfb5,0x3fedbfb5,
0x3fed0000,0xbf440000,0xbf444000,0x3fedc000,0xbf44bfb5,0xbfed3fb5,0x3fedbfb5,0x3f44bfb5,0x3ff5bfb5,0x3fe2bfb5,0x3f153fb5,0xbf713fb5,
0xbfc6bec8,0x3fffbffb,0x3fa2bffb,0x3e493ec8,0xbe493fed,0x3fc6bfed,0xbfff3f44,0x3fa2bf44,0x3fe2bfd5,0x3f15bf8e,0x3f713f8e,0x3ff5bfd5,
0x3fd50000,0x3ec80000,0xbf8e4000,0xbffb4000,0x3ec8bfed,0x3f8ebf44,0x3ffbbf44,0xbfd53fed,0xbffb3fb5,0x3fd5bfb5,0xbec8bfb5,0xbf8e3fb5,
0x3f8e3f44,0x3ffbbfed,0xbfd53fed,0xbec83f44,0x3e493fb5,0xbfa23fb5,0xbfff3fb5,0xbfc63fb5,0x3ff5bfd5,0xbf713f8e,0x3f153f8e,0xbfe23fd5,
0xbf71bf44,0xbf153f44,0x3fe2bfed,0xbff53fed,0xbfc63ffb,0xbe493ec8,0xbfa2bec8,0xbfff3ffb,0xc0004000,0xbfb54000,0x0,0x3fb50000,
0xc0004000,0x3fb50000,0x0,0x3fb5c000,0xc0004000,0x3fb5c000,0x0,0xbfb50000,0xc0004000,0xbfb50000,0x0,0xbfb54000,
0xbfa23fb5,0x3e493fb5,0x3fc6bfb5,0x3fffbfb5,0xbf713f8e,0x3ff5bfd5,0x3fe2bfd5,0xbf15bf8e,0xbf153f44,0xbf71bf44,0x3ff5bfed,0xbfe23fed,
0xbe493ec8,0xbfc63ffb,0x3fffbffb,0x3fa23ec8,0x3ec80000,0x3fd50000,0x3ffbc000,0x3f8ec000,0x3f8ebf44,0x3ec8bfed,0x3fd5bfed,0xbffb3f44,
0x3fd5bfb5,0xbffb3fb5,0x3f8ebfb5,0x3ec83fb5,0x3ffbbfed,0x3f8e3f44,0x3ec8bf44,0x3fd5bfed,0x3fe2bfb5,0x3ff5bfb5,0x3f71bfb5,0xbf15bfb5,
0x3fffbffb,0xbfc6bec8,0xbe49bec8,0xbfa23ffb,0x3fc6bfed,0xbe493fed,0xbfa23f44,0x3fffbf44,0x3f15bf8e,0x3fe2bfd5,0xbff53fd5,0xbf71bf8e,
0x3fedc000,0x3f44c000,0xbf440000,0xbfed0000,0x3f44bfb5,0xbfed3fb5,0xbfed3fb5,0x3f443fb5,0xbf440000,0x3fed0000,0xbfed4000,0x3f44c000,
0xbfed3fb5,0xbf44bfb5,0xbf443fb5,0xbfed3fb5,0x3f15bfb5,0xbf71bfb5,0xbff53fb5,0xbfe23fb5,0xbfa23ec8,0xbe493ffb,0xbfc63ffb,0x3fffbec8,
0xbfff3fed,0x3fa2bfed,0x3e493f44,0xbfc6bf44,0xbf713fd5,0xbff53f8e,0x3fe2bf8e,0x3f153fd5,0xbf8e0000,0xbffb0000,0xbfd54000,0xbec84000,
0xbffb3fed,0x3fd53f44,0x3ec83f44,0x3f8ebfed,0xbec83fb5,0xbf8ebfb5,0x3ffbbfb5,0xbfd53fb5,0x3fd5bf44,0x3ec83fed,0x3f8ebfed,0x3ffbbf44,
0xbfff3fb5,0xbfc63fb5,0xbe493fb5,0x3fa23fb5,0xbf153fd5,0x3fe2bf8e,0x3ff5bf8e,0xbf71bfd5,0x3fe2bf44,0xbff53f44,0x3f71bfed,0x3f153fed,
0x3fa2bffb,0x3fffbec8,0xbfc63ec8,0xbe49bffb,0x4000,0x3fb54000,0x40000000,0x3fb50000,0xc000,0xbfb50000,0xc0000000,0x3fb54000,
0x4000,0xbfb5c000,0x40000000,0xbfb50000,0xc000,0x3fb50000,0xc0000000,0xbfb5c000,0x3fc63fb5,0x3fff3fb5,0x3fa2bfb5,0xbe49bfb5,
0xbfe2bf8e,0x3f153fd5,0xbf713fd5,0x3ff53f8e,0x3ff53f44,0xbfe2bf44,0x3f15bfed,0x3f713fed,0xbfffbec8,0xbfa2bffb,0xbe493ffb,0xbfc6bec8,
0x3ffb0000,0x3f8e0000,0xbec8c000,0xbfd5c000,0xbfd53f44,0x3ffb3fed,0x3f8e3fed,0x3ec8bf44,0x3f8ebfb5,0x3ec83fb5,0xbfd5bfb5,0x3ffb3fb5,
0xbec83fed,0xbfd5bf44,0x3ffb3f44,0x3f8e3fed,0x3f71bfb5,0xbf15bfb5,0xbfe2bfb5,0xbff5bfb5,0x3e493ffb,0x3fa23ec8,0x3fff3ec8,0xbfc6bffb,
0xbfa2bfed,0x3fff3fed,0xbfc63f44,0x3e49bf44,0x3ff53f8e,0x3f713fd5,0x3f15bfd5,0x3fe23f8e,0xbf44c000,0xbfedc000,0xbfed0000,0xbf440000,
0x3fed3fb5,0xbf44bfb5,0x3f44bfb5,0xbfedbfb5,0xbfed0000,0x3f440000,0x3f444000,0xbfedc000,0x3f44bfb5,0x3fed3fb5,0xbfedbfb5,0xbf44bfb5,
0xbff5bfb5,0xbfe2bfb5,0xbf153fb5,0x3f713fb5,0x3fc6bec8,0xbfffbffb,0xbfa2bffb,0xbe493ec8,0x3e493fed,0xbfc6bfed,0x3fff3f44,0xbfa2bf44,
0xbfe2bfd5,0xbf15bf8e,0xbf713f8e,0xbff5bfd5,0xbfd50000,0xbec80000,0x3f8e4000,0x3ffb4000,0xbec8bfed,0xbf8ebf44,0xbffbbf44,0x3fd53fed,
0x3ffb3fb5,0xbfd5bfb5,0x3ec8bfb5,0x3f8e3fb5,0xbf8e3f44,0xbffbbfed,0x3fd53fed,0x3ec83f44,0xbe493fb5,0x3fa23fb5,0x3fff3fb5,0x3fc63fb5,
0xbff5bfd5,0x3f713f8e,0xbf153f8e,0x3fe23fd5,0x3f71bf44,0x3f153f44,0xbfe2bfed,0x3ff53fed,0x3fc63ffb,0x3e493ec8,0x3fa2bec8,0x3fff3ffb,
0x40004000,0x3fb54000,0x0,0xbfb50000,0x40004000,0xbfb50000,0x0,0xbfb5c000,0x40004000,0xbfb5c000,0x0,0x3fb50000,
0x40004000,0x3fb50000,0x0,0x3fb54000,0xbe490000,0xbfc60000,0xbfffc000,0xbfa2c000,0xbf15bec8,0xbf71bffb,0xbff5bffb,0x3fe23ec8,
0xbf71bf44,0x3ff53f44,0xbfe2bfed,0x3f153fed,0xbfa2bf8e,0x3e493fd5,0xbfc6bfd5,0xbfffbf8e,0xbffbc000,0xbf8ec000,0x3ec80000,0x3fd50000,
0xbfd5bfed,0x3ffb3f44,0x3f8e3f44,0x3ec83fed,0xbf8ebfb5,0xbec83fb5,0x3fd53fb5,0xbffbbfb5,0xbec8bf44,0xbfd5bfed,0x3ffb3fed,0x3f8ebf44,
0x3f150000,0x3fe20000,0x3ff54000,0x3f714000,0x3fc63f8e,0xbe493fd5,0x3fa23fd5,0xbfffbf8e,0x3fff3fed,0xbfc6bfed,0x3e493f44,0x3fa2bf44,
0x3fe23ffb,0x3ff53ec8,0xbf71bec8,0x3f153ffb,0x3fed4000,0x3f444000,0xbf440000,0xbfed0000,0x3f443fb5,0xbfedbfb5,0xbfedbfb5,0x3f44bfb5,
0xbf440000,0x3fed0000,0xbfedc000,0x3f444000,0xbfedbfb5,0xbf443fb5,0xbf44bfb5,0xbfedbfb5,0xbf710000,0xbff50000,0xbfe2c000,0xbf15c000,
0xbfffbfd5,0x3fa2bf8e,0xbe49bf8e,0x3fc63fd5,0xbfa2bfed,0xbe493fed,0x3fc63f44,0xbfffbf44,0x3f15bec8,0xbf71bffb,0x3ff53ffb,0x3fe2bec8,
0xbfd5c000,0xbec8c000,0x3f8e0000,0x3ffb0000,0x3ec8bf44,0x3f8e3fed,0x3ffb3fed,0xbfd53f44,0x3ffb3fb5,0xbfd5bfb5,0x3ec83fb5,0x3f8ebfb5,
0x3f8e3fed,0x3ffb3f44,0xbfd5bf44,0xbec83fed,0x3fa20000,0x3fff0000,0x3fc64000,0x3e494000,0x3fe23ffb,0xbff53ec8,0xbf713ec8,0xbf15bffb,
0xbf153f44,0x3fe2bf44,0xbff5bfed,0x3f713fed,0xbfffbfd5,0xbfc63f8e,0x3e49bf8e,0xbfa2bfd5,0x4000,0xbfb54000,0xc0000000,0xbfb50000,
0xc000,0x3fb50000,0x40000000,0xbfb54000,0x4000,0x3fb5c000,0xc0000000,0x3fb50000,0xc000,0xbfb50000,0x40000000,0x3fb5c000,
0xbfff0000,0xbfa20000,0x3e49c000,0x3fc6c000,0x3ff53ec8,0xbfe23ffb,0xbf153ffb,0xbf71bec8,0xbfe2bf44,0x3f153f44,0x3f71bfed,0xbff53fed,
0x3fc63f8e,0x3fffbfd5,0xbfa23fd5,0x3e493f8e,0x3ec8c000,0x3fd5c000,0x3ffb0000,0x3f8e0000,0xbf8e3fed,0xbec8bf44,0xbfd5bf44,0x3ffbbfed,
0x3fd5bfb5,0xbffb3fb5,0x3f8e3fb5,0x3ec8bfb5,0xbffb3f44,0xbf8e3fed,0xbec8bfed,0xbfd53f44,0x3ff50000,0x3f710000,0xbf154000,0xbfe24000,
0xbfa2bf8e,0x3fffbfd5,0x3fc6bfd5,0xbe493f8e,0x3e493fed,0x3fa2bfed,0xbfff3f44,0x3fc6bf44,0x3f71bffb,0xbf15bec8,0x3fe23ec8,0x3ff5bffb,
0xbf444000,0xbfed4000,0xbfed0000,0xbf440000,0x3fedbfb5,0xbf443fb5,0x3f443fb5,0xbfed3fb5,0xbfed0000,0x3f440000,0x3f44c000,0xbfed4000,
0x3f443fb5,0x3fedbfb5,0xbfed3fb5,0xbf443fb5,0xbfe20000,0xbf150000,0x3f71c000,0x3ff5c000,0x3e493fd5,0xbfc63f8e,0xbfff3f8e,0x3fa2bfd5,
0x3fc6bfed,0xbfff3fed,0x3fa23f44,0x3e49bf44,0xbff53ec8,0xbfe23ffb,0x3f15bffb,0xbf713ec8,0x3f8ec000,0x3ffbc000,0x3fd50000,0x3ec80000,
0xbffb3f44,0x3fd5bfed,0x3ec8bfed,0x3f8ebf44,0x3ec83fb5,0x3f8ebfb5,0xbffb3fb5,0x3fd5bfb5,0x3fd5bfed,0x3ec8bf44,0x3f8e3f44,0x3ffbbfed,
0x3fc60000,0x3e490000,0xbfa24000,0xbfff4000,0x3f71bffb,0x3f15bec8,0x3fe2bec8,0xbff53ffb,0xbff53f44,0x3f71bf44,0x3f15bfed,0xbfe23fed,
0xbe493fd5,0x3fa2bf8e,0xbfff3f8e,0xbfc63fd5,0xc0004000,0xbfb54000,0x0,0x3fb50000,0xc0004000,0x3fb50000,0x0,0x3fb5c000,
0xc0004000,0x3fb5c000,0x0,0xbfb50000,0xc0004000,0xbfb50000,0x0,0xbfb54000,0x3e490000,0x3fc60000,0x3fffc000,0x3fa2c000,
0x3f15bec8,0x3f71bffb,0x3ff5bffb,0xbfe23ec8,0x3f71bf44,0xbff53f44,0x3fe2bfed,0xbf153fed,0x3fa2bf8e,0xbe493fd5,0x3fc6bfd5,0x3fffbf8e,
0x3ffbc000,0x3f8ec000,0xbec80000,0xbfd50000,0x3fd5bfed,0xbffb3f44,0xbf8e3f44,0xbec83fed,0x3f8ebfb5,0x3ec83fb5,0xbfd53fb5,0x3ffbbfb5,
0x3ec8bf44,0x3fd5bfed,0xbffb3fed,0xbf8ebf44,0xbf150000,0xbfe20000,0xbff54000,0xbf714000,0xbfc63f8e,0x3e493fd5,0xbfa23fd5,0x3fffbf8e,
0xbfff3fed,0x3fc6bfed,0xbe493f44,0xbfa2bf44,0xbfe23ffb,0xbff53ec8,0x3f71bec8,0xbf153ffb,0xbfed4000,0xbf444000,0x3f440000,0x3fed0000,
0xbf443fb5,0x3fedbfb5,0x3fedbfb5,0xbf44bfb5,0x3f440000,0xbfed0000,0x3fedc000,0xbf444000,0x3fedbfb5,0x3f443fb5,0x3f44bfb5,0x3fedbfb5,
0x3f710000,0x3ff50000,0x3fe2c000,0x3f15c000,0x3fffbfd5,0xbfa2bf8e,0x3e49bf8e,0xbfc63fd5,0x3fa2bfed,0x3e493fed,0xbfc63f44,0x3fffbf44,
0xbf15bec8,0x3f71bffb,0xbff53ffb,0xbfe2bec8,0x3fd5c000,0x3ec8c000,0xbf8e0000,0xbffb0000,0xbec8bf44,0xbf8e3fed,0xbffb3fed,0x3fd53f44,
0xbffb3fb5,0x3fd5bfb5,0xbec83fb5,0xbf8ebfb5,0xbf8e3fed,0xbffb3f44,0x3fd5bf44,0x3ec83fed,0xbfa20000,0xbfff0000,0xbfc64000,0xbe494000,
0xbfe23ffb,0x3ff53ec8,0x3f713ec8,0x3f15bffb,0x3f153f44,0xbfe2bf44,0x3ff5bfed,0xbf713fed,0x3fffbfd5,0x3fc63f8e,0xbe49bf8e,0x3fa2bfd5,
0x4000,0x3fb54000,0x40000000,0x3fb50000,0xc000,0xbfb50000,0xc0000000,0x3fb54000,0x4000,0xbfb5c000,0x40000000,0xbfb50000,
0xc000,0x3fb50000,0xc0000000,0xbfb5c000,0x3fff0000,0x3fa20000,0xbe49c000,0xbfc6c000,0xbff53ec8,0x3fe23ffb,0x3f153ffb,0x3f71bec8,
0x3fe2bf44,0xbf153f44,0xbf71bfed,0x3ff53fed,0xbfc63f8e,0xbfffbfd5,0x3fa23fd5,0xbe493f8e,0xbec8c000,0xbfd5c000,0xbffb0000,0xbf8e0000,
0x3f8e3fed,0x3ec8bf44,0x3fd5bf44,0xbffbbfed,0xbfd5bfb5,0x3ffb3fb5,0xbf8e3fb5,0xbec8bfb5,0x3ffb3f44,0x3f8e3fed,0x3ec8bfed,0x3fd53f44,
0xbff50000,0xbf710000,0x3f154000,0x3fe24000,0x3fa2bf8e,0xbfffbfd5,0xbfc6bfd5,0x3e493f8e,0xbe493fed,0xbfa2bfed,0x3fff3f44,0xbfc6bf44,
0xbf71bffb,0x3f15bec8,0xbfe23ec8,0xbff5bffb,0x3f444000,0x3fed4000,0x3fed0000,0x3f440000,0xbfedbfb5,0x3f443fb5,0xbf443fb5,0x3fed3fb5,
0x3fed0000,0xbf440000,0xbf44c000,0x3fed4000,0xbf443fb5,0xbfedbfb5,0x3fed3fb5,0x3f443fb5,0x3fe20000,0x3f150000,0xbf71c000,0xbff5c000,
0xbe493fd5,0x3fc63f8e,0x3fff3f8e,0xbfa2bfd5,0xbfc6bfed,0x3fff3fed,0xbfa23f44,0xbe49bf44,0x3ff53ec8,0x3fe23ffb,0xbf15bffb,0x3f713ec8,
0xbf8ec000,0xbffbc000,0xbfd50000,0xbec80000,0x3ffb3f44,0xbfd5bfed,0xbec8bfed,0xbf8ebf44,0xbec83fb5,0xbf8ebfb5,0x3ffb3fb5,0xbfd5bfb5,
0xbfd5bfed,0xbec8bf44,0xbf8e3f44,0xbffbbfed,0xbfc60000,0xbe490000,0x3fa24000,0x3fff4000,0xbf71bffb,0xbf15bec8,0xbfe2bec8,0x3ff53ffb,
0x3ff53f44,0xbf71bf44,0xbf15bfed,0x3fe23fed,0x3e493fd5,0xbfa2bf8e,0x3fff3f8e,0x3fc63fd5,0x40004000,0x3fb54000,0x0,0xbfb50000,
0x40004000,0xbfb50000,0x0,0xbfb5c000,0x40004000,0xbfb5c000,0x0,0x3fb50000,0x40004000,0x3fb50000,0x0,0x3fb54000,
0xbfc6bfb5,0xbfffbfb5,0xbfa2bfb5,0x3e49bfb5,0xbfe2bfd5,0x3f15bf8e,0xbf71bf8e,0x3ff53fd5,0xbff5bfed,0x3fe23fed,0xbf15bf44,0xbf713f44,
0xbfffbffb,0xbfa23ec8,0xbe49bec8,0xbfc6bffb,0x3ec80000,0x3fd50000,0x3ffb4000,0x3f8e4000,0x3f8e3f44,0x3ec83fed,0x3fd53fed,0xbffbbf44,
0x3fd53fb5,0xbffbbfb5,0x3f8e3fb5,0x3ec8bfb5,0x3ffb3fed,0x3f8ebf44,0x3ec83f44,0x3fd53fed,0x3f713fb5,0xbf153fb5,0xbfe2bfb5,0xbff5bfb5,
0xbe493ec8,0xbfa2bffb,0xbfffbffb,0x3fc6bec8,0xbfa2bf44,0x3fff3f44,0xbfc6bfed,0x3e493fed,0xbff5bfd5,0xbf713f8e,0xbf15bf8e,0xbfe2bfd5,
0xbfedc000,0xbf44c000,0x3f440000,0x3fed0000,0xbf44bfb5,0x3fed3fb5,0x3fed3fb5,0xbf443fb5,0x3f440000,0xbfed0000,0x3fed4000,0xbf44c000,
0x3fed3fb5,0x3f44bfb5,0x3f443fb5,0x3fed3fb5,0x3ff53fb5,0x3fe23fb5,0x3f153fb5,0xbf713fb5,0x3fc63ffb,0xbfffbec8,0xbfa2bec8,0xbe49bffb,
0xbe493f44,0x3fc6bf44,0xbfffbfed,0x3fa23fed,0xbfe2bf8e,0xbf153fd5,0xbf71bfd5,0xbff5bf8e,0xbf8e0000,0xbffb0000,0xbfd5c000,0xbec8c000,
0xbffbbfed,0x3fd5bf44,0x3ec8bf44,0x3f8e3fed,0xbec8bfb5,0xbf8e3fb5,0x3ffb3fb5,0xbfd5bfb5,0x3fd53f44,0x3ec8bfed,0x3f8e3fed,0x3ffb3f44,
0xbe49bfb5,0x3fa2bfb5,0x3fff3fb5,0x3fc63fb5,0x3ff53f8e,0xbf713fd5,0x3f153fd5,0xbfe2bf8e,0x3f713fed,0x3f15bfed,0xbfe2bf44,0x3ff53f44,
0xbfc6bec8,0xbe493ffb,0xbfa2bffb,0xbfffbec8,0x4000,0xbfb54000,0xc0000000,0xbfb50000,0xc000,0x3fb50000,0x40000000,0xbfb54000,
0x4000,0x3fb5c000,0xc0000000,0x3fb50000,0xc000,0xbfb50000,0x40000000,0x3fb5c000,0xbfa2bfb5,0x3e49bfb5,0x3fc6bfb5,0x3fffbfb5,
0x3f713fd5,0xbff53f8e,0xbfe23f8e,0x3f15bfd5,0xbf15bfed,0xbf713fed,0x3ff5bf44,0xbfe23f44,0x3e493ffb,0x3fc6bec8,0xbfff3ec8,0xbfa23ffb,
0x3ffb0000,0x3f8e0000,0xbec84000,0xbfd54000,0xbfd5bf44,0x3ffbbfed,0x3f8ebfed,0x3ec83f44,0x3f8e3fb5,0x3ec8bfb5,0xbfd53fb5,0x3ffbbfb5,
0xbec8bfed,0xbfd53f44,0x3ffbbf44,0x3f8ebfed,0xbfe23fb5,0xbff53fb5,0xbf71bfb5,0x3f15bfb5,0x3fffbec8,0xbfc63ffb,0xbe493ffb,0xbfa23ec8,
0xbfc6bf44,0x3e493f44,0x3fa2bfed,0xbfff3fed,0x3f153fd5,0x3fe2bf8e,0xbff53f8e,0xbf713fd5,0x3f44c000,0x3fedc000,0x3fed0000,0x3f440000,
0xbfed3fb5,0x3f44bfb5,0xbf44bfb5,0x3fedbfb5,0x3fed0000,0xbf440000,0xbf444000,0x3fedc000,0xbf44bfb5,0xbfed3fb5,0x3fedbfb5,0x3f44bfb5,
0x3f153fb5,0xbf713fb5,0xbff53fb5,0xbfe23fb5,0x3fa2bffb,0x3e493ec8,0x3fc63ec8,0xbfff3ffb,0xbfff3f44,0x3fa2bf44,0x3e49bfed,0xbfc63fed,
0x3f713f8e,0x3ff5bfd5,0xbfe23fd5,0xbf153f8e,0xbfd50000,0xbec80000,0x3f8ec000,0x3ffbc000,0xbec83fed,0xbf8e3f44,0xbffb3f44,0x3fd5bfed,
0x3ffbbfb5,0xbfd53fb5,0x3ec83fb5,0x3f8ebfb5,0xbf8ebf44,0xbffb3fed,0x3fd5bfed,0x3ec8bf44,0x3fffbfb5,0x3fc6bfb5,0x3e493fb5,0xbfa23fb5,
0xbf15bf8e,0x3fe2bfd5,0x3ff5bfd5,0xbf713f8e,0xbfe23fed,0x3ff5bfed,0xbf71bf44,0xbf153f44,0x3fa23ec8,0x3fffbffb,0xbfc63ffb,0xbe493ec8,
0xc0004000,0xbfb54000,0x0,0x3fb50000,0xc0004000,0x3fb50000,0x0,0x3fb5c000,0xc0004000,0x3fb5c000,0x0,0xbfb50000,
0xc0004000,0xbfb50000,0x0,0xbfb54000,0x3fc6bfb5,0x3fffbfb5,0x3fa2bfb5,0xbe49bfb5,0x3fe2bfd5,0xbf15bf8e,0x3f71bf8e,0xbff53fd5,
0x3ff5bfed,0xbfe23fed,0x3f15bf44,0x3f713f44,0x3fffbffb,0x3fa23ec8,0x3e49bec8,0x3fc6bffb,0xbec80000,0xbfd50000,0xbffb4000,0xbf8e4000,
0xbf8e3f44,0xbec83fed,0xbfd53fed,0x3ffbbf44,0xbfd53fb5,0x3ffbbfb5,0xbf8e3fb5,0xbec8bfb5,0xbffb3fed,0xbf8ebf44,0xbec83f44,0xbfd53fed,
0xbf713fb5,0x3f153fb5,0x3fe2bfb5,0x3ff5bfb5,0x3e493ec8,0x3fa2bffb,0x3fffbffb,0xbfc6bec8,0x3fa2bf44,0xbfff3f44,0x3fc6bfed,0xbe493fed,
0x3ff5bfd5,0x3f713f8e,0x3f15bf8e,0x3fe2bfd5,0x3fedc000,0x3f44c000,0xbf440000,0xbfed0000,0x3f44bfb5,0xbfed3fb5,0xbfed3fb5,0x3f443fb5,
0xbf440000,0x3fed0000,0xbfed4000,0x3f44c000,0xbfed3fb5,0xbf44bfb5,0xbf443fb5,0xbfed3fb5,0xbff53fb5,0xbfe23fb5,0xbf153fb5,0x3f713fb5,
0xbfc63ffb,0x3fffbec8,0x3fa2bec8,0x3e49bffb,0x3e493f44,0xbfc6bf44,0x3fffbfed,0xbfa23fed,0x3fe2bf8e,0x3f153fd5,0x3f71bfd5,0x3ff5bf8e,
0x3f8e0000,0x3ffb0000,0x3fd5c000,0x3ec8c000,0x3ffbbfed,0xbfd5bf44,0xbec8bf44,0xbf8e3fed,0x3ec8bfb5,0x3f8e3fb5,0xbffb3fb5,0x3fd5bfb5,
0xbfd53f44,0xbec8bfed,0xbf8e3fed,0xbffb3f44,0x3e49bfb5,0xbfa2bfb5,0xbfff3fb5,0xbfc63fb5,0xbff53f8e,0x3f713fd5,0xbf153fd5,0x3fe2bf8e,
0xbf713fed,0xbf15bfed,0x3fe2bf44,0xbff53f44,0x3fc6bec8,0x3e493ffb,0x3fa2bffb,0x3fffbec8,0x4000,0x3fb54000,0x40000000,0x3fb50000,
0xc000,0xbfb50000,0xc0000000,0x3fb54000,0x4000,0xbfb5c000,0x40000000,0xbfb50000,0xc000,0x3fb50000,0xc0000000,0xbfb5c000,
0x3fa2bfb5,0xbe49bfb5,0xbfc6bfb5,0xbfffbfb5,0xbf713fd5,0x3ff53f8e,0x3fe23f8e,0xbf15bfd5,0x3f15bfed,0x3f713fed,0xbff5bf44,0x3fe23f44,
0xbe493ffb,0xbfc6bec8,0x3fff3ec8,0x3fa23ffb,0xbffb0000,0xbf8e0000,0x3ec84000,0x3fd54000,0x3fd5bf44,0xbffbbfed,0xbf8ebfed,0xbec83f44,
0xbf8e3fb5,0xbec8bfb5,0x3fd53fb5,0xbffbbfb5,0x3ec8bfed,0x3fd53f44,0xbffbbf44,0xbf8ebfed,0x3fe23fb5,0x3ff53fb5,0x3f71bfb5,0xbf15bfb5,
0xbfffbec8,0x3fc63ffb,0x3e493ffb,0x3fa23ec8,0x3fc6bf44,0xbe493f44,0xbfa2bfed,0x3fff3fed,0xbf153fd5,0xbfe2bf8e,0x3ff53f8e,0x3f713fd5,
0xbf44c000,0xbfedc000,0xbfed0000,0xbf440000,0x3fed3fb5,0xbf44bfb5,0x3f44bfb5,0xbfedbfb5,0xbfed0000,0x3f440000,0x3f444000,0xbfedc000,
0x3f44bfb5,0x3fed3fb5,0xbfedbfb5,0xbf44bfb5,0xbf153fb5,0x3f713fb5,0x3ff53fb5,0x3fe23fb5,0xbfa2bffb,0xbe493ec8,0xbfc63ec8,0x3fff3ffb,
0x3fff3f44,0xbfa2bf44,0xbe49bfed,0x3fc63fed,0xbf713f8e,0xbff5bfd5,0x3fe23fd5,0x3f153f8e,0x3fd50000,0x3ec80000,0xbf8ec000,0xbffbc000,
0x3ec83fed,0x3f8e3f44,0x3ffb3f44,0xbfd5bfed,0xbffbbfb5,0x3fd53fb5,0xbec83fb5,0xbf8ebfb5,0x3f8ebf44,0x3ffb3fed,0xbfd5bfed,0xbec8bf44,
0xbfffbfb5,0xbfc6bfb5,0xbe493fb5,0x3fa23fb5,0x3f15bf8e,0xbfe2bfd5,0xbff5bfd5,0x3f713f8e,0x3fe23fed,0xbff5bfed,0x3f71bf44,0x3f153f44,
0xbfa23ec8,0xbfffbffb,0x3fc63ffb,0x3e493ec8,0x80003f80,0x3f800000,0x80003f80,0x3f800000,0x80003f80,0x3f800000,0x80003f80,0x3f800000,
0x80003f80,0x3f800000,0x80003f80,0x3f800000,0x80003f80,0x3f800000,0x80003f80,0x3f800000,0x80003f80,0x3f800000,0x8000bf80,0xbf800000,
0x3f353f35,0x3f35bf35,0xbf35bf35,0xbf353f35,0x3f800000,0xbf80,0xbf800000,0x3f80,0x3f35bf35,0xbf35bf35,0xbf353f35,0x3f353f35,
0x80003f80,0x3f800000,0x80003f80,0x3f800000,0x3f800000,0xbf80,0x3f800000,0xbf80,0x8000bf80,0xbf800000,0x8000bf80,0xbf800000,
0xbf800000,0x3f80,0xbf800000,0x3f80,0x80003f80,0x3f800000,0x8000bf80,0xbf800000,0x3f35bf35,0xbf35bf35,0xbf353f35,0x3f353f35,
0xbf800000,0x3f80,0x3f800000,0xbf80,0x3f353f35,0x3f35bf35,0xbf35bf35,0xbf353f35,0x80003f80,0x3f800000,0x80003f80,0x3f800000,
0x8000bf80,0xbf800000,0x8000bf80,0xbf800000,0x80003f80,0x3f800000,0x80003f80,0x3f800000,0x8000bf80,0xbf800000,0x8000bf80,0xbf800000,
0x80003f80,0x3f800000,0x8000bf80,0xbf800000,0xbf35bf35,0xbf353f35,0x3f353f35,0x3f35bf35,0x3f800000,0xbf80,0xbf800000,0x3f80,
0xbf353f35,0x3f353f35,0x3f35bf35,0xbf35bf35,0x80003f80,0x3f800000,0x80003f80,0x3f800000,0xbf800000,0x3f80,0xbf800000,0x3f80,
0x8000bf80,0xbf800000,0x8000bf80,0xbf800000,0x3f800000,0xbf80,0x3f800000,0xbf80,0x80003f80,0x3f800000,0x8000bf80,0xbf800000,
0xbf353f35,0x3f353f35,0x3f35bf35,0xbf35bf35,0xbf800000,0x3f80,0x3f800000,0xbf80,0xbf35bf35,0xbf353f35,0x3f353f35,0x3f35bf35,
0x3f803f80,0x80008000,0x80008000,0xbf80bf80,0x3f803f80,0x80008000,0x80008000,0xbf80bf80,0x3f803f80,0x80008000,0x80008000,0xbf80bf80,
0x3f803f80,0x80008000,0x80008000,0xbf80bf80,0x3f353f80,0x3f358000,0x3f358000,0xbf35bf80,0xbf350000,0x3f353f80,0x3f353f80,0x3f358000,
0xbf35bf80,0xbf358000,0xbf358000,0x3f353f80,0x3f350000,0xbf35bf80,0xbf35bf80,0xbf358000,0x3f80,0x3f808000,0x3f808000,0x8000bf80,
0xbf80,0xbf808000,0xbf808000,0x80003f80,0x3f80,0x3f808000,0x3f808000,0x8000bf80,0xbf80,0xbf808000,0xbf808000,0x80003f80,
0xbf353f80,0x3f358000,0x3f358000,0x3f35bf80,0x3f350000,0x3f35bf80,0x3f35bf80,0xbf358000,0x3f35bf80,0xbf358000,0xbf358000,0xbf353f80,
0xbf350000,0xbf353f80,0xbf353f80,0x3f358000,0xbf803f80,0x80008000,0x80008000,0x3f80bf80,0xbf803f80,0x80008000,0x80008000,0x3f80bf80,
0xbf803f80,0x80008000,0x80008000,0x3f80bf80,0xbf803f80,0x80008000,0x80008000,0x3f80bf80,0xbf353f80,0xbf358000,0xbf358000,0x3f35bf80,
0x3f350000,0xbf353f80,0xbf353f80,0xbf358000,0x3f35bf80,0x3f358000,0x3f358000,0xbf353f80,0xbf350000,0x3f35bf80,0x3f35bf80,0x3f358000,
0x3f80,0xbf808000,0xbf808000,0x8000bf80,0xbf80,0x3f808000,0x3f808000,0x80003f80,0x3f80,0xbf808000,0xbf808000,0x8000bf80,
0xbf80,0x3f808000,0x3f808000,0x80003f80,0x3f353f80,0xbf358000,0xbf358000,0xbf35bf80,0xbf350000,0xbf35bf80,0xbf35bf80,0x3f358000,
0xbf35bf80,0x3f358000,0x3f358000,0x3f353f80,0x3f350000,0x3f353f80,0x3f353f80,0xbf358000,0x3f800000,0x0,0x3f800000,0x0,
0x3f800000,0x0,0x3f800000,0x0,0x3f800000,0x0,0x3f800000,0x0,0x3f800000,0x0,0x3f800000,0x0,
0x3f800000,0x0,0x3f7fb10f,0xbd48fb30,0x3f7ec46d,0xbdc8bd36,0x3f7d3aac,0xbe164083,0x3f7b14be,0xbe47c5c2,0x3f7853f8,0xbe78cfcc,
0x3f74fa0b,0xbe94a031,0x3f710908,0xbeac7cd4,0x3f800000,0x0,0x3f7ec46d,0xbdc8bd36,0x3f7b14be,0xbe47c5c2,0x3f74fa0b,0xbe94a031,
0x3f6c835e,0xbec3ef15,0x3f61c598,0xbef15aea,0x3f54db31,0xbf0e39da,0x3f45e403,0xbf226799,0x3f800000,0x0,0x3f7d3aac,0xbe164083,
0x3f74fa0b,0xbe94a031,0x3f676bd8,0xbedae880,0x3f54db31,0xbf0e39da,0x3f3daef9,0xbf2beb4a,0x3f226799,0xbf45e403,0x3f039c3d,0xbf5b941a,
0x3f800000,0x0,0x3f7b14be,0xbe47c5c2,0x3f6c835e,0xbec3ef15,0x3f54db31,0xbf0e39da,0x3f3504f3,0xbf3504f3,0x3f0e39da,0xbf54db31,
0x3ec3ef15,0xbf6c835e,0x3e47c5c2,0xbf7b14be,0x3f800000,0x0,0x3f7853f8,0xbe78cfcc,0x3f61c598,0xbef15aea,0x3f3daef9,0xbf2beb4a,
0x3f0e39da,0xbf54db31,0x3eac7cd4,0xbf710908,0x3dc8bd36,0xbf7ec46d,0xbe164083,0xbf7d3aac,0x3f800000,0x0,0x3f74fa0b,0xbe94a031,
0x3f54db31,0xbf0e39da,0x3f226799,0xbf45e403,0x3ec3ef15,0xbf6c835e,0x3dc8bd36,0xbf7ec46d,0xbe47c5c2,0xbf7b14be,0xbef15aea,0xbf61c598,
0x3f800000,0x0,0x3f710908,0xbeac7cd4,0x3f45e403,0xbf226799,0x3f039c3d,0xbf5b941a,0x3e47c5c2,0xbf7b14be,0xbe164083,0xbf7d3aac,
0xbef15aea,0xbf61c598,0xbf3daef9,0xbf2beb4a,0x3f800000,0x0,0x3f800000,0x0,0x3f800000,0x0,0x3f800000,0x0,
0x3f800000,0x0,0x3f800000,0x0,0x3f800000,0x0,0x3f800000,0x0,0x3f6c835e,0xbec3ef15,0x3f676bd8,0xbedae880,
0x3f61c598,0xbef15aea,0x3f5b941a,0xbf039c3d,0x3f54db31,0xbf0e39da,0x3f4d9f02,0xbf187fc0,0x3f45e403,0xbf226799,0x3f3daef9,0xbf2beb4a,
0x3f3504f3,0xbf3504f3,0x3f226799,0xbf45e403,0x3f0e39da,0xbf54db31,0x3ef15aea,0xbf61c598,0x3ec3ef15,0xbf6c835e,0x3e94a031,0xbf74fa0b,
0x3e47c5c2,0xbf7b14be,0x3dc8bd36,0xbf7ec46d,0x3ec3ef15,0xbf6c835e,0x3e78cfcc,0xbf7853f8,0x3dc8bd36,0xbf7ec46d,0xbd48fb30,0xbf7fb10f,
0xbe47c5c2,0xbf7b14be,0xbeac7cd4,0xbf710908,0xbef15aea,0xbf61c598,0xbf187fc0,0xbf4d9f02,0x0,0xbf800000,0xbe47c5c2,0xbf7b14be,
0xbec3ef15,0xbf6c835e,0xbf0e39da,0xbf54db31,0xbf3504f3,0xbf3504f3,0xbf54db31,0xbf0e39da,0xbf6c835e,0xbec3ef15,0xbf7b14be,0xbe47c5c2,
0xbec3ef15,0xbf6c835e,0xbf187fc0,0xbf4d9f02,0xbf45e403,0xbf226799,0xbf676bd8,0xbedae880,0xbf7b14be,0xbe47c5c2,0xbf7fb10f,0x3d48fb30,
0xbf74fa0b,0x3e94a031,0xbf5b941a,0x3f039c3d,0xbf3504f3,0xbf3504f3,0xbf61c598,0xbef15aea,0xbf7b14be,0xbe47c5c2,0xbf7ec46d,0x3dc8bd36,
0xbf6c835e,0x3ec3ef15,0xbf45e403,0x3f226799,0xbf0e39da,0x3f54db31,0xbe94a031,0x3f74fa0b,0xbf6c835e,0xbec3ef15,0xbf7fb10f,0xbd48fb30,
0xbf74fa0b,0x3e94a031,0xbf4d9f02,0x3f187fc0,0xbf0e39da,0x3f54db31,0xbe78cfcc,0x3f7853f8,0x3dc8bd36,0x3f7ec46d,0x3edae880,0x3f676bd8,
0x80003f80,0x3f800000,0x3f800000,0xbf80,0x3ec43f6d,0x3f6dbec4,0x3f6dbec4,0xbec4bf6d,0x3f353f35,0x3f35bf35,0x3f35bf35,0xbf35bf35,
0x3f6d3ec4,0x3ec4bf6d,0x3ec4bf6d,0xbf6dbec4,0x80003f80,0x3f800000,0xbf800000,0x3f80,0x3f6d3ec4,0x3ec4bf6d,0xbec43f6d,0x3f6d3ec4,
0x3f35bf35,0xbf35bf35,0x3f353f35,0x3f35bf35,0xbec4bf6d,0xbf6d3ec4,0x3f6dbec4,0xbec4bf6d,0x80003f80,0x3f800000,0x3f800000,0xbf80,
0x3f6dbec4,0xbec4bf6d,0xbec4bf6d,0xbf6d3ec4,0xbf35bf35,0xbf353f35,0xbf353f35,0x3f353f35,0xbec43f6d,0x3f6d3ec4,0x3f6d3ec4,0x3ec4bf6d,
0x80003f80,0x3f800000,0xbf800000,0x3f80,0x3ec4bf6d,0xbf6dbec4,0x3f6d3ec4,0x3ec4bf6d,0xbf353f35,0x3f353f35,0xbf35bf35,0xbf353f35,
0x3f6dbec4,0xbec4bf6d,0x3ec43f6d,0x3f6dbec4,0x80003f80,0x3f800000,0x3f800000,0xbf80,0xbec4bf6d,0xbf6d3ec4,0xbf6d3ec4,0x3ec43f6d,
0x3f353f35,0x3f35bf35,0x3f35bf35,0xbf35bf35,0xbf6dbec4,0xbec43f6d,0xbec43f6d,0x3f6d3ec4,0x80003f80,0x3f800000,0xbf800000,0x3f80,
0xbf6dbec4,0xbec43f6d,0x3ec4bf6d,0xbf6dbec4,0x3f35bf35,0xbf35bf35,0x3f353f35,0x3f35bf35,0x3ec43f6d,0x3f6dbec4,0xbf6d3ec4,0x3ec43f6d,
0x80003f80,0x3f800000,0x3f800000,0xbf80,0xbf6d3ec4,0x3ec43f6d,0x3ec43f6d,0x3f6dbec4,0xbf35bf35,0xbf353f35,0xbf353f35,0x3f353f35,
0x3ec4bf6d,0xbf6dbec4,0xbf6dbec4,0xbec43f6d,0x80003f80,0x3f800000,0xbf800000,0x3f80,0xbec43f6d,0x3f6d3ec4,0xbf6dbec4,0xbec43f6d,
0xbf353f35,0x3f353f35,0xbf35bf35,0xbf353f35,0xbf6d3ec4,0x3ec43f6d,0xbec4bf6d,0xbf6d3ec4,0x3f803f80,0x80008000,0x80008000,0xbf80bf80,
0x3f803f80,0x80008000,0x80008000,0xbf80bf80,0x3f803f80,0x80008000,0x80008000,0xbf80bf80,0x3f803f80,0x80008000,0x80008000,0xbf80bf80,
0x3ec43f6d,0x3f6d3ec4,0x3f6d3ec4,0xbec4bf6d,0xbf6dbec4,0x3ec43f6d,0x3ec43f6d,0x3f6d3ec4,0xbec4bf6d,0xbf6dbec4,0xbf6dbec4,0x3ec43f6d,
0x3f6d3ec4,0xbec4bf6d,0xbec4bf6d,0xbf6dbec4,0xbf353f35,0x3f353f35,0x3f353f35,0x3f35bf35,0x3f35bf35,0xbf35bf35,0xbf35bf35,0xbf353f35,
0xbf353f35,0x3f353f35,0x3f353f35,0x3f35bf35,0x3f35bf35,0xbf35bf35,0xbf35bf35,0xbf353f35,0xbf6d3ec4,0xbec43f6d,0xbec43f6d,0x3f6dbec4,
0xbec43f6d,0x3f6dbec4,0x3f6dbec4,0x3ec4bf6d,0x3f6dbec4,0x3ec4bf6d,0x3ec4bf6d,0xbf6d3ec4,0x3ec4bf6d,0xbf6d3ec4,0xbf6d3ec4,0xbec43f6d,
0x0,0xbf803f80,0xbf803f80,0x80008000,0x0,0xbf803f80,0xbf803f80,0x80008000,0x0,0xbf803f80,0xbf803f80,0x80008000,
0x0,0xbf803f80,0xbf803f80,0x80008000,0x3f6dbec4,0xbec43f6d,0xbec43f6d,0xbf6d3ec4,0x3ec4bf6d,0x3f6dbec4,0x3f6dbec4,0xbec43f6d,
0xbf6d3ec4,0x3ec4bf6d,0x3ec4bf6d,0x3f6dbec4,0xbec43f6d,0xbf6d3ec4,0xbf6d3ec4,0x3ec4bf6d,0x3f35bf35,0x3f353f35,0x3f353f35,0xbf353f35,
0xbf353f35,0xbf35bf35,0xbf35bf35,0x3f35bf35,0x3f35bf35,0x3f353f35,0x3f353f35,0xbf353f35,0xbf353f35,0xbf35bf35,0xbf35bf35,0x3f35bf35,
0xbec4bf6d,0x3f6d3ec4,0x3f6d3ec4,0x3ec43f6d,0x3f6d3ec4,0x3ec43f6d,0x3ec43f6d,0xbf6dbec4,0x3ec43f6d,0xbf6dbec4,0xbf6dbec4,0xbec4bf6d,
0xbf6dbec4,0xbec4bf6d,0xbec4bf6d,0x3f6d3ec4,0x3f800000,0x0,0x3f7fec43,0xbcc90ab0,0x3f7fb10f,0xbd48fb30,0x3f7f4e6d,0xbd96a905,
0x3f7ec46d,0xbdc8bd36,0x3f7e1324,0xbdfab273,0x3f7d3aac,0xbe164083,0x3f7c3b28,0xbe2f10a2,0x3f800000,0x0,0x3f7f4e6d,0xbd96a905,
0x3f7d3aac,0xbe164083,0x3f79c79d,0xbe605c13,0x3f74fa0b,0xbe94a031,0x3f6ed89e,0xbeb8442a,0x3f676bd8,0xbedae880,0x3f5ebe05,0xbefc5d27,
0x3f800000,0x0,0x3f7e1324,0xbdfab273,0x3f7853f8,0xbe78cfcc,0x3f6ed89e,0xbeb8442a,0x3f61c598,0xbef15aea,0x3f514d3d,0xbf13682a,
0x3f3daef9,0xbf2beb4a,0x3f273656,0xbf41d870,0x3f800000,0x0,0x3f7c3b28,0xbe2f10a2,0x3f710908,0xbeac7cd4,0x3f5ebe05,0xbefc5d27,
0x3f45e403,0xbf226799,0x3f273656,0xbf41d870,0x3f039c3d,0xbf5b941a,0x3eb8442a,0xbf6ed89e,0x3f800000,0x0,0x3f79c79d,0xbe605c13,
0x3f676bd8,0xbedae880,0x3f49d112,0xbf1d7fd1,0x3f226799,0xbf45e403,0x3ee63375,0xbf64aa59,0x3e78cfcc,0xbf7853f8,0x3cc90ab0,0xbf7fec43,
0x3f800000,0x0,0x3f76ba07,0xbe888e93,0x3f5b941a,0xbf039c3d,0x3f3085bb,0xbf396842,0x3ef15aea,0xbf61c598,0x3e605c13,0xbf79c79d,
0xbd48fb30,0xbf7fb10f,0xbea09ae5,0xbf731447,0x3f800000,0x0,0x3f731447,0xbea09ae5,0x3f4d9f02,0xbf187fc0,0x3f13682a,0xbf514d3d,
0x3e94a031,0xbf74fa0b,0xbcc90ab0,0xbf7fec43,0xbeac7cd4,0xbf710908,0xbf1d7fd1,0xbf49d112,0x3f800000,0x0,0x3f6ed89e,0xbeb8442a,
0x3f3daef9,0xbf2beb4a,0x3ee63375,0xbf64aa59,0x3dc8bd36,0xbf7ec46d,0xbe888e93,0xbf76ba07,0xbf187fc0,0xbf4d9f02,0xbf584853,0xbf08f59b,
0x3f7b14be,0xbe47c5c2,0x3f79c79d,0xbe605c13,0x3f7853f8,0xbe78cfcc,0x3f76ba07,0xbe888e93,0x3f74fa0b,0xbe94a031,0x3f731447,0xbea09ae5,
0x3f710908,0xbeac7cd4,0x3f6ed89e,0xbeb8442a,0x3f54db31,0xbf0e39da,0x3f49d112,0xbf1d7fd1,0x3f3daef9,0xbf2beb4a,0x3f3085bb,0xbf396842,
0x3f226799,0xbf45e403,0x3f13682a,0xbf514d3d,0x3f039c3d,0xbf5b941a,0x3ee63375,0xbf64aa59,0x3f0e39da,0xbf54db31,0x3ee63375,0xbf64aa59,
0x3eac7cd4,0xbf710908,0x3e605c13,0xbf79c79d,0x3dc8bd36,0xbf7ec46d,0xbcc90ab0,0xbf7fec43,0xbe164083,0xbf7d3aac,0xbe888e93,0xbf76ba07,
0x3e47c5c2,0xbf7b14be,0x3cc90ab0,0xbf7fec43,0xbe164083,0xbf7d3aac,0xbea09ae5,0xbf731447,0xbef15aea,0xbf61c598,0xbf1d7fd1,0xbf49d112,
0xbf3daef9,0xbf2beb4a,0xbf584853,0xbf08f59b,0xbe47c5c2,0xbf7b14be,0xbecf7bca,0xbf6a09a7,0xbf187fc0,0xbf4d9f02,0xbf41d870,0xbf273656,
0xbf61c598,0xbef15aea,0xbf76ba07,0xbe888e93,0xbf7fb10f,0xbd48fb30,0xbf7c3b28,0x3e2f10a2,0xbf0e39da,0xbf54db31,0xbf41d870,0xbf273656,
0xbf676bd8,0xbedae880,0xbf7c3b28,0xbe2f10a2,0xbf7ec46d,0x3dc8bd36,0xbf6ed89e,0x3eb8442a,0xbf4d9f02,0x3f187fc0,0xbf1d7fd1,0x3f49d112,
0xbf54db31,0xbf0e39da,0xbf76ba07,0xbe888e93,0xbf7fb10f,0x3d48fb30,0xbf6ed89e,0x3eb8442a,0xbf45e403,0x3f226799,0xbf08f59b,0x3f584853,
0xbe78cfcc,0x3f7853f8,0x3d96a905,0x3f7f4e6d,0xbf7b14be,0xbe47c5c2,0xbf7c3b28,0x3e2f10a2,0xbf5b941a,0x3f039c3d,0xbf1d7fd1,0x3f49d112,
0xbe94a031,0x3f74fa0b,0x3d96a905,0x3f7f4e6d,0x3edae880,0x3f676bd8,0x3f396842,0x3f3085bb,0x80003f80,0x80003f80,0x80003f80,0x80003f80,
0x80003f80,0x80003f80,0x80003f80,0x80003f80,0x80003f80,0x80003f80,0x80003f80,0x80003f80,0x80003f80,0x80003f80,0x80003f80,0x80003f80,
0x3f800000,0x3f800000,0x3f800000,0x3f800000,0x3f800000,0x3f800000,0x3f800000,0x3f800000,0x3f800000,0x3f800000,0x3f800000,0x3f800000,
0x3f800000,0x3f800000,0x3f800000,0x3f800000,0x80003f80,0x3f353f35,0x80003f80,0x3f353f35,0x3f800000,0x3f35bf35,0x3f800000,0x3f35bf35,
0x8000bf80,0xbf35bf35,0x8000bf80,0xbf35bf35,0xbf800000,0xbf353f35,0xbf800000,0xbf353f35,0x3f800000,0x3f35bf35,0x3f800000,0x3f35bf35,
0xbf80,0xbf35bf35,0xbf80,0xbf35bf35,0xbf800000,0xbf353f35,0xbf800000,0xbf353f35,0x3f80,0x3f353f35,0x3f80,0x3f353f35,
0x80003f80,0x3f800000,0x80003f80,0x3f800000,0x8000bf80,0xbf800000,0x8000bf80,0xbf800000,0x80003f80,0x3f800000,0x80003f80,0x3f800000,
0x8000bf80,0xbf800000,0x8000bf80,0xbf800000,0x3f800000,0xbf80,0x3f800000,0xbf80,0xbf800000,0x3f80,0xbf800000,0x3f80,
0x3f800000,0xbf80,0x3f800000,0xbf80,0xbf800000,0x3f80,0xbf800000,0x3f80,0x80003f80,0x3f35bf35,0x80003f80,0x3f35bf35,
0xbf800000,0x3f353f35,0xbf800000,0x3f353f35,0x8000bf80,0xbf353f35,0x8000bf80,0xbf353f35,0x3f800000,0xbf35bf35,0x3f800000,0xbf35bf35,
0x3f800000,0xbf35bf35,0x3f800000,0xbf35bf35,0x3f80,0x3f35bf35,0x3f80,0x3f35bf35,0xbf800000,0x3f353f35,0xbf800000,0x3f353f35,
0xbf80,0xbf353f35,0xbf80,0xbf353f35,0x80003f80,0x3ec43f6d,0x8000bf80,0xbec4bf6d,0x3f353f35,0x3f6d3ec4,0xbf35bf35,0xbf6dbec4,
0x3f800000,0x3f6dbec4,0xbf800000,0xbf6d3ec4,0x3f35bf35,0x3ec4bf6d,0xbf353f35,0xbec43f6d,0x3f800000,0x3f6dbec4,0xbf800000,0xbf6d3ec4,
0x3f35bf35,0x3ec4bf6d,0xbf353f35,0xbec43f6d,0xbf80,0xbec4bf6d,0x3f80,0x3ec43f6d,0xbf35bf35,0xbf6dbec4,0x3f353f35,0x3f6d3ec4,
0x80003f80,0x3f6d3ec4,0x8000bf80,0xbf6dbec4,0x3f35bf35,0xbec4bf6d,0xbf353f35,0x3ec43f6d,0xbf800000,0xbec43f6d,0x3f800000,0x3ec4bf6d,
0x3f353f35,0x3f6dbec4,0xbf35bf35,0xbf6d3ec4,0x3f800000,0x3ec4bf6d,0xbf800000,0xbec43f6d,0xbf35bf35,0xbf6d3ec4,0x3f353f35,0x3f6dbec4,
0x3f80,0x3f6d3ec4,0xbf80,0xbf6dbec4,0x3f35bf35,0xbec4bf6d,0xbf353f35,0x3ec43f6d,0x80003f80,0x3f6dbec4,0x8000bf80,0xbf6d3ec4,
0xbf35bf35,0xbec43f6d,0x3f353f35,0x3ec4bf6d,0x3f800000,0xbec4bf6d,0xbf800000,0x3ec43f6d,0xbf353f35,0x3f6d3ec4,0x3f35bf35,0xbf6dbec4,
0x3f800000,0xbec4bf6d,0xbf800000,0x3ec43f6d,0xbf353f35,0x3f6d3ec4,0x3f35bf35,0xbf6dbec4,0xbf80,0xbf6d3ec4,0x3f80,0x3f6dbec4,
0x3f353f35,0x3ec4bf6d,0xbf35bf35,0xbec43f6d,0x80003f80,0x3ec4bf6d,0x8000bf80,0xbec43f6d,0xbf353f35,0x3f6dbec4,0x3f35bf35,0xbf6d3ec4,
0xbf800000,0x3f6d3ec4,0x3f800000,0xbf6dbec4,0xbf35bf35,0x3ec43f6d,0x3f353f35,0xbec4bf6d,0x3f800000,0xbf6dbec4,0xbf800000,0x3f6d3ec4,
0x3f353f35,0xbec4bf6d,0xbf35bf35,0x3ec43f6d,0x3f80,0x3ec4bf6d,0xbf80,0xbec43f6d,0xbf353f35,0x3f6dbec4,0x3f35bf35,0xbf6d3ec4,
0x80003f80,0x8000bf80,0x80003f80,0x8000bf80,0x80003f80,0x8000bf80,0x80003f80,0x8000bf80,0x80003f80,0x8000bf80,0x80003f80,0x8000bf80,
0x80003f80,0x8000bf80,0x80003f80,0x8000bf80,0x3f800000,0xbf800000,0x3f800000,0xbf800000,0x3f800000,0xbf800000,0x3f800000,0xbf800000,
0x3f800000,0xbf800000,0x3f800000,0xbf800000,0x3f800000,0xbf800000,0x3f800000,0xbf800000,0x80003f80,0xbf35bf35,0x80003f80,0xbf35bf35,
0x3f800000,0xbf353f35,0x3f800000,0xbf353f35,0x8000bf80,0x3f353f35,0x8000bf80,0x3f353f35,0xbf800000,0x3f35bf35,0xbf800000,0x3f35bf35,
0x3f800000,0xbf353f35,0x3f800000,0xbf353f35,0xbf80,0x3f353f35,0xbf80,0x3f353f35,0xbf800000,0x3f35bf35,0xbf800000,0x3f35bf35,
0x3f80,0xbf35bf35,0x3f80,0xbf35bf35,0x80003f80,0xbf800000,0x80003f80,0xbf800000,0x8000bf80,0x3f800000,0x8000bf80,0x3f800000,
0x80003f80,0xbf800000,0x80003f80,0xbf800000,0x8000bf80,0x3f800000,0x8000bf80,0x3f800000,0x3f800000,0x3f80,0x3f800000,0x3f80,
0xbf800000,0xbf80,0xbf800000,0xbf80,0x3f800000,0x3f80,0x3f800000,0x3f80,0xbf800000,0xbf80,0xbf800000,0xbf80,
0x80003f80,0xbf353f35,0x80003f80,0xbf353f35,0xbf800000,0xbf35bf35,0xbf800000,0xbf35bf35,0x8000bf80,0x3f35bf35,0x8000bf80,0x3f35bf35,
0x3f800000,0x3f353f35,0x3f800000,0x3f353f35,0x3f800000,0x3f353f35,0x3f800000,0x3f353f35,0x3f80,0xbf353f35,0x3f80,0xbf353f35,
0xbf800000,0xbf35bf35,0xbf800000,0xbf35bf35,0xbf80,0x3f35bf35,0xbf80,0x3f35bf35,0x80003f80,0xbec4bf6d,0x8000bf80,0x3ec43f6d,
0x3f353f35,0xbf6dbec4,0xbf35bf35,0x3f6d3ec4,0x3f800000,0xbf6d3ec4,0xbf800000,0x3f6dbec4,0x3f35bf35,0xbec43f6d,0xbf353f35,0x3ec4bf6d,
0x3f800000,0xbf6d3ec4,0xbf800000,0x3f6dbec4,0x3f35bf35,0xbec43f6d,0xbf353f35,0x3ec4bf6d,0xbf80,0x3ec43f6d,0x3f80,0xbec4bf6d,
0xbf35bf35,0x3f6d3ec4,0x3f353f35,0xbf6dbec4,0x80003f80,0xbf6dbec4,0x8000bf80,0x3f6d3ec4,0x3f35bf35,0x3ec43f6d,0xbf353f35,0xbec4bf6d,
0xbf800000,0x3ec4bf6d,0x3f800000,0xbec43f6d,0x3f353f35,0xbf6d3ec4,0xbf35bf35,0x3f6dbec4,0x3f800000,0xbec43f6d,0xbf800000,0x3ec4bf6d,
0xbf35bf35,0x3f6dbec4,0x3f353f35,0xbf6d3ec4,0x3f80,0xbf6dbec4,0xbf80,0x3f6d3ec4,0x3f35bf35,0x3ec43f6d,0xbf353f35,0xbec4bf6d,
0x80003f80,0xbf6d3ec4,0x8000bf80,0x3f6dbec4,0xbf35bf35,0x3ec4bf6d,0x3f353f35,0xbec43f6d,0x3f800000,0x3ec43f6d,0xbf800000,0xbec4bf6d,
0xbf353f35,0xbf6dbec4,0x3f35bf35,0x3f6d3ec4,0x3f800000,0x3ec43f6d,0xbf800000,0xbec4bf6d,0xbf353f35,0xbf6dbec4,0x3f35bf35,0x3f6d3ec4,
0xbf80,0x3f6dbec4,0x3f80,0xbf6d3ec4,0x3f353f35,0xbec43f6d,0xbf35bf35,0x3ec4bf6d,0x80003f80,0xbec43f6d,0x8000bf80,0x3ec4bf6d,
0xbf353f35,0xbf6d3ec4,0x3f35bf35,0x3f6dbec4,0xbf800000,0xbf6dbec4,0x3f800000,0x3f6d3ec4,0xbf35bf35,0xbec4bf6d,0x3f353f35,0x3ec43f6d,
0x3f800000,0x3f6d3ec4,0xbf800000,0xbf6dbec4,0x3f353f35,0x3ec43f6d,0xbf35bf35,0xbec4bf6d,0x3f80,0xbec43f6d,0xbf80,0x3ec4bf6d,
0xbf353f35,0xbf6d3ec4,0x3f35bf35,0x3f6dbec4,
};
constexpr int TB_F = 0, TB_E = 512, TB_P2 = 1024;

enum { C_EP = 0, C_Z1 = 32, C_Z2 = 96, C_H3 = 128, C_U = 160, C_X = 288, C_TOTAL = 512 };
struct Scratch {
  unsigned cnt[C_TOTAL];
  uint32_t moda[8 * 2 * D_];
  uint32_t mod[4 * D_ + 256];
  uint32_t z1[120 * 5120];
  uint32_t z2[128 * 4800];
  uint8_t h3[32 * 18 * 4096];
  uint8_t u[72 * D_ * 128];
};
__device__ __align__(1024) Scratch g_s;

#define PF2 8
#define PF2K 16
#define HOLDA 5
#define GOAT 0
#define H3W 0
#define X1K 10
#define PEEK 1
#ifndef NV1
#define NV1 12
#endif
#ifndef NV2
#define NV2 20
#endif
#define GDEP 0
#define TRK0 50
#define W0N 3
#define TRKC 350
#define J2 6
#define MODPOS 2
#define LNM 0x30
constexpr int NB15 = 192 + 32 * __builtin_popcount(LNM);
#define HD1 200
#define STRESS 0
#define NG1 1

#define FAILCNT(k) do {} while (0)
#define CK(k) do {} while (0)
#define CKX(k) do {} while (0)
#define TS(k) do {} while (0)
#define TSC(k) do {} while (0)
struct Maps { CUtensorMap z1, z2[2], w1a, w1b, h3, w2, wf[4], wm; };
struct Params {
  const __nv_bfloat16 *x, *c, *wmod;
  Scratch* s;
  const uint4* tab;
  const __nv_bfloat16 *wr, *wi, *w1, *w2, *b1, *b2;
  uint32_t* out;
};

__device__ __forceinline__ uint32_t smem_u32(const void* p) { return (uint32_t)__cvta_generic_to_shared(p); }
__device__ __forceinline__ void mbar_init(uint32_t b, int c) { asm volatile("mbarrier.init.shared::cta.b64 [%0], %1;" ::"r"(b), "r"(c)); }
__device__ __forceinline__ void mbar_expect(uint32_t b, int bytes) { asm volatile("mbarrier.arrive.expect_tx.shared::cta.b64 _, [%0], %1;" ::"r"(b), "r"(bytes) : "memory"); }
__device__ __forceinline__ void mbar_arrive(uint32_t b) { asm volatile("mbarrier.arrive.shared::cta.b64 _, [%0];" ::"r"(b) : "memory"); }
#define MBAR_WAIT(SEM)                                                                                                         \
  asm volatile("{\n.reg .pred p;\n.reg .u32 it;\nmov.u32 it, 0;\nW:\nmbarrier.try_wait.parity" SEM ".shared::cta.b64 p, [%0], %1;\n" \
               "@p bra.uni D;\nadd.u32 it, it, 1;\nsetp.lt.u32 p, it, 0x400000;\n@p bra.uni W;\ntrap;\nD:\n}" ::"r"(b), "r"(ph) : "memory")
__device__ __forceinline__ void mbar_wait(uint32_t b, int ph) { MBAR_WAIT(""); }
__device__ __forceinline__ uint32_t mbar_test(uint32_t b, int ph) {
  uint32_t ok;
  asm volatile("{\n.reg .pred p;\nmbarrier.test_wait.parity.shared::cta.b64 p, [%1], %2;\nselp.u32 %0, 1, 0, p;\n}\n" : "=r"(ok) : "r"(b), "r"(ph) : "memory");
  return ok;
}
__device__ __forceinline__ void tma2d(uint32_t dst, const CUtensorMap* m, int c0, int c1, uint32_t bar) {
  asm volatile("cp.async.bulk.tensor.2d.shared::cluster.global.mbarrier::complete_tx::bytes [%0], [%1, {%3, %4}], [%2];" ::"r"(dst), "l"(m), "r"(bar), "r"(c0), "r"(c1) : "memory");
}
__device__ __forceinline__ uint64_t pol_ef() { uint64_t p; asm("createpolicy.fractional.L2::evict_first.b64 %0, 1.0;" : "=l"(p)); return p; }
__device__ __forceinline__ void tma3d_ef(uint32_t dst, const CUtensorMap* m, int c1, int c2, uint32_t bar) {
  asm volatile("cp.async.bulk.tensor.3d.shared::cluster.global.mbarrier::complete_tx::bytes.L2::cache_hint [%0], [%1, {%3, %4, %5}], [%2], %6;" ::"r"(dst), "l"(m), "r"(bar), "r"(0), "r"(c1), "r"(c2), "l"(pol_ef()) : "memory");
}
__device__ __forceinline__ void tma4d_ef(uint32_t dst, const CUtensorMap* m, int c1, int c2, int c3, uint32_t bar) {
  asm volatile("cp.async.bulk.tensor.4d.shared::cluster.global.mbarrier::complete_tx::bytes.L2::cache_hint [%0], [%1, {%3, %7, %4, %5}], [%2], %6;" ::"r"(dst), "l"(m), "r"(bar), "r"(0), "r"(c2), "r"(c3), "l"(pol_ef()), "r"(c1) : "memory");
}
__device__ __forceinline__ void bulk_ld(uint32_t dst, const void* src, int bytes, uint32_t bar) {
  asm volatile("cp.async.bulk.shared::cluster.global.mbarrier::complete_tx::bytes [%0], [%1], %2, [%3];" ::"r"(dst), "l"(src), "r"(bytes), "r"(bar) : "memory");
}
__device__ __forceinline__ void bulk_st(void* dst, uint32_t src, int bytes) {
  asm volatile("cp.async.bulk.global.shared::cta.bulk_group [%0], [%1], %2;" ::"l"(dst), "r"(src), "r"(bytes) : "memory");
}
__device__ __forceinline__ void tma_st2d(const CUtensorMap* m, uint32_t src, int c0, int c1) {
  asm volatile("cp.async.bulk.tensor.2d.global.shared::cta.bulk_group [%0, {%2, %3}], [%1];" ::"l"(m), "r"(src), "r"(c0), "r"(c1) : "memory");
}
__device__ __forceinline__ void tma_st3d(const CUtensorMap* m, uint32_t src, int c0, int c1, int c2) {
  asm volatile("cp.async.bulk.tensor.3d.global.shared::cta.bulk_group [%0, {%2, %3, %4}], [%1];" ::"l"(m), "r"(src), "r"(c0), "r"(c1), "r"(c2) : "memory");
}
__device__ __forceinline__ void bulk_commit_wait_read() {
  asm volatile("cp.async.bulk.commit_group;" ::: "memory");
  asm volatile("cp.async.bulk.wait_group.read 0;" ::: "memory");
}
__device__ __forceinline__ void bulk_commit_wait() {
  asm volatile("cp.async.bulk.commit_group;" ::: "memory");
  asm volatile("cp.async.bulk.wait_group 0;" ::: "memory");
}
__device__ __forceinline__ void prefetch_l2(const void* p, int bytes) {
  asm volatile("cp.async.bulk.prefetch.L2.global [%0], %1;" ::"l"(p), "r"(bytes) : "memory");
}
__device__ __forceinline__ void wg_fence() { asm volatile("wgmma.fence.sync.aligned;" ::: "memory"); }
__device__ __forceinline__ void wg_commit() { asm volatile("wgmma.commit_group.sync.aligned;" ::: "memory"); }
template <int N> __device__ __forceinline__ void wg_wait() { asm volatile("wgmma.wait_group.sync.aligned %0;" ::"n"(N) : "memory"); }
template <int N> __device__ __forceinline__ void reg_fence(float (&d)[N]) {
#pragma unroll
  for (int i = 0; i < N; i++) asm volatile("" : "+f"(d[i])::"memory");
}
__device__ __forceinline__ void fence_async_smem() { asm volatile("fence.proxy.async.shared::cta;" ::: "memory"); }
__device__ __forceinline__ void fence_async_glb() { asm volatile("fence.proxy.async.global;" ::: "memory"); }
__device__ __forceinline__ uint32_t ld_rlx(const void* p) { uint32_t v; asm volatile("ld.relaxed.gpu.global.b32 %0, [%1];" : "=r"(v) : "l"(p) : "memory"); return v; }
__device__ __forceinline__ uint2 ld_rlx2(const void* p) { uint2 v; asm volatile("ld.relaxed.gpu.global.v2.b32 {%0,%1}, [%2];" : "=r"(v.x), "=r"(v.y) : "l"(p) : "memory"); return v; }
__device__ __forceinline__ uint4 ld_rlx4(const void* p) { uint4 v; asm volatile("ld.relaxed.gpu.global.v4.b32 {%0,%1,%2,%3}, [%4];" : "=r"(v.x), "=r"(v.y), "=r"(v.z), "=r"(v.w) : "l"(p) : "memory"); return v; }
__device__ __forceinline__ uint32_t ld_nc(const void* p) { uint32_t v; asm volatile("ld.global.nc.L1::no_allocate.b32 %0, [%1];" : "=r"(v) : "l"(p) : "memory"); return v; }
__device__ __forceinline__ uint4 ld_nc4(const void* p) { uint4 v; asm volatile("ld.global.nc.v4.b32 {%0,%1,%2,%3}, [%4];" : "=r"(v.x), "=r"(v.y), "=r"(v.z), "=r"(v.w) : "l"(p) : "memory"); return v; }
__device__ __forceinline__ uint32_t lds(uint32_t a) { uint32_t v; asm volatile("ld.shared.b32 %0, [%1];" : "=r"(v) : "r"(a) : "memory"); return v; }
__device__ __forceinline__ uint2 lds2(uint32_t a) { uint2 v; asm volatile("ld.shared.v2.b32 {%0,%1}, [%2];" : "=r"(v.x), "=r"(v.y) : "r"(a) : "memory"); return v; }
__device__ __forceinline__ uint4 lds4(uint32_t a) { uint4 v; asm volatile("ld.shared.v4.b32 {%0,%1,%2,%3}, [%4];" : "=r"(v.x), "=r"(v.y), "=r"(v.z), "=r"(v.w) : "r"(a) : "memory"); return v; }
__device__ __forceinline__ float lds_bf(uint32_t a) { uint32_t v; asm volatile("ld.shared.u16 %0, [%1];" : "=r"(v) : "r"(a) : "memory"); return __uint_as_float(v << 16); }
__device__ __forceinline__ void sts(uint32_t a, uint32_t v) { asm volatile("st.shared.b32 [%0], %1;" ::"r"(a), "r"(v) : "memory"); }
__device__ __forceinline__ void sts2(uint32_t a, uint32_t v0, uint32_t v1) { asm volatile("st.shared.v2.b32 [%0], {%1,%2};" ::"r"(a), "r"(v0), "r"(v1) : "memory"); }
__device__ __forceinline__ void sts4(uint32_t a, uint32_t v0, uint32_t v1, uint32_t v2, uint32_t v3) { asm volatile("st.shared.v4.b32 [%0], {%1,%2,%3,%4};" ::"r"(a), "r"(v0), "r"(v1), "r"(v2), "r"(v3) : "memory"); }
__device__ __forceinline__ void bar_sync(int id, int n) { asm volatile("bar.sync %0, %1;" ::"r"(id), "r"(n) : "memory"); }
__device__ __forceinline__ void bar_arrive(int id, int n) { asm volatile("bar.arrive %0, %1;" ::"r"(id), "r"(n) : "memory"); }
__device__ __forceinline__ void red_add(unsigned* p, unsigned v) { asm volatile("red.relaxed.gpu.global.add.u32 [%0], %1;" ::"l"(p), "r"(v) : "memory"); }
__device__ __forceinline__ bool any(bool p) { return __any_sync(0xffffffffu, p); }
__device__ __forceinline__ void pause(unsigned clks) {
  asm volatile("{\n.reg .pred p;\n.reg .u32 a, b;\nmov.u32 a, %%clock;\nW:\nmov.u32 b, %%clock;\nsub.u32 b, b, a;\nsetp.lt.s32 p, b, %0;\n@p bra.uni W;\n}" ::"r"(clks) : "memory");
}
__device__ __forceinline__ void red_bf16x8(uint32_t* p, uint32_t a, uint32_t b, uint32_t c, uint32_t d) {
  asm volatile("red.relaxed.gpu.global.add.noftz.v4.bf16x2 [%0], {%1,%2,%3,%4};" ::"l"(p), "r"(a), "r"(b), "r"(c), "r"(d) : "memory");
}
__device__ __forceinline__ void red_bf16x4(uint32_t* p, uint32_t a, uint32_t b) {
  asm volatile("red.relaxed.gpu.global.add.noftz.v2.bf16x2 [%0], {%1,%2};" ::"l"(p), "r"(a), "r"(b) : "memory");
}
constexpr int SPIN_MAX = 1 << 20;
__device__ __forceinline__ uint32_t ld_acq(const void* p) { uint32_t v; asm volatile("ld.acquire.gpu.global.b32 %0, [%1];" : "=r"(v) : "l"(p) : "memory"); return v; }
template <bool ACQ = false> __device__ __forceinline__ void wait_cnt(const unsigned* p, unsigned target) {
  int it = 0;
  while (any((int)((ACQ ? ld_acq(p) : ld_rlx(p)) - target) < 0) && ++it < SPIN_MAX) {}
}
__device__ __forceinline__ uint32_t pack_bf16(float lo, float hi) { uint32_t r; asm("cvt.rn.bf16x2.f32 %0, %1, %2;" : "=r"(r) : "f"(hi), "f"(lo)); return r; }
__device__ __forceinline__ float bf_lo(uint32_t v) { return __uint_as_float(v << 16); }
__device__ __forceinline__ float bf_hi(uint32_t v) { return __uint_as_float(v & 0xffff0000u); }
__device__ __forceinline__ uint32_t hadd2(uint32_t a, uint32_t b) { uint32_t r; asm("add.rn.bf16x2 %0, %1, %2;" : "=r"(r) : "r"(a), "r"(b)); return r; }
__device__ __forceinline__ uint32_t hmul2(uint32_t a, uint32_t b) { uint32_t r; asm("mul.rn.bf16x2 %0, %1, %2;" : "=r"(r) : "r"(a), "r"(b)); return r; }
__device__ __forceinline__ uint32_t hfma2(uint32_t a, uint32_t b, uint32_t c) { uint32_t r; asm("fma.rn.bf16x2 %0, %1, %2, %3;" : "=r"(r) : "r"(a), "r"(b), "r"(c)); return r; }
__device__ __forceinline__ float rbf(float x) { uint32_t r; asm("cvt.rn.bf16x2.f32 %0, %1, %2;" : "=r"(r) : "f"(x), "f"(0.0f)); return __uint_as_float(r); }
__device__ __forceinline__ void stmatrix4(uint32_t a, uint32_t r0, uint32_t r1, uint32_t r2, uint32_t r3) {
  asm volatile("stmatrix.sync.aligned.m8n8.x4.shared.b16 [%0], {%1,%2,%3,%4};" ::"r"(a), "r"(r0), "r"(r1), "r"(r2), "r"(r3) : "memory");
}
__device__ __forceinline__ void stmatrix2(uint32_t a, uint32_t r0, uint32_t r1) {
  asm volatile("stmatrix.sync.aligned.m8n8.x2.shared.b16 [%0], {%1,%2};" ::"r"(a), "r"(r0), "r"(r1) : "memory");
}
__device__ __forceinline__ void stmatrix4t(uint32_t a, uint32_t r0, uint32_t r1, uint32_t r2, uint32_t r3) {
  asm volatile("stmatrix.sync.aligned.m8n8.x4.trans.shared.b16 [%0], {%1,%2,%3,%4};" ::"r"(a), "r"(r0), "r"(r1), "r"(r2), "r"(r3) : "memory");
}
__device__ __forceinline__ uint32_t movm(uint32_t a) { uint32_t r; asm("movmatrix.sync.aligned.m8n8.trans.b16 %0, %1;" : "=r"(r) : "r"(a)); return r; }
template <bool ACC> __device__ __forceinline__ void mma16(float* d, uint32_t a0, uint32_t a1, uint32_t a2, uint32_t a3, uint32_t b0, uint32_t b1) {
  if (ACC) asm("mma.sync.aligned.m16n8k16.row.col.f32.bf16.bf16.f32 {%0,%1,%2,%3}, {%4,%5,%6,%7}, {%8,%9}, {%0,%1,%2,%3};"
               : "+f"(d[0]), "+f"(d[1]), "+f"(d[2]), "+f"(d[3]) : "r"(a0), "r"(a1), "r"(a2), "r"(a3), "r"(b0), "r"(b1));
  else asm("mma.sync.aligned.m16n8k16.row.col.f32.bf16.bf16.f32 {%0,%1,%2,%3}, {%4,%5,%6,%7}, {%8,%9}, {%10,%10,%10,%10};"
           : "=f"(d[0]), "=f"(d[1]), "=f"(d[2]), "=f"(d[3]) : "r"(a0), "r"(a1), "r"(a2), "r"(a3), "r"(b0), "r"(b1), "f"(0.f));
}
__device__ __forceinline__ uint32_t pin(uint32_t v) { uint32_t r; asm volatile("shfl.sync.bfly.b32 %0, %1, 0, 31, 0xffffffff;" : "=r"(r) : "r"(v)); return r; }
template <class T> __device__ __forceinline__ T* pin(T* p) {
  const uint64_t a = reinterpret_cast<uint64_t>(p);
  return reinterpret_cast<T*>((uint64_t)pin((uint32_t)a) | ((uint64_t)pin((uint32_t)(a >> 32)) << 32));
}
__device__ __forceinline__ uint32_t upin(uint32_t v) { return __shfl_sync(0xffffffffu, v, 0); }
template <class T> __device__ __forceinline__ T* upin(T* p) {
  const uint64_t a = reinterpret_cast<uint64_t>(p);
  return reinterpret_cast<T*>((uint64_t)upin((uint32_t)a) | ((uint64_t)upin((uint32_t)(a >> 32)) << 32));
}
__device__ __forceinline__ bool elect() {
  uint32_t p;
  asm volatile("{\n.reg .pred P;\nelect.sync _|P, 0xffffffff;\nselp.u32 %0, 1, 0, P;\n}" : "=r"(p));
  return p;
}
__device__ __forceinline__ uint32_t set_tag(uint32_t w, uint32_t tag) { uint32_t r; asm("lop3.b32 %0, %1, 0xfffffffe, %2, 0xea;" : "=r"(r) : "r"(w), "r"(tag)); return r; }
__device__ __forceinline__ uint32_t bitsel(uint32_t w, uint32_t m, uint32_t o) { uint32_t r; asm("lop3.b32 %0, %1, %2, %3, 0xe2;" : "=r"(r) : "r"(w), "r"(m), "r"(o)); return r; }
__device__ __forceinline__ uint32_t or3(uint32_t a, uint32_t b, uint32_t c) { uint32_t r; asm("lop3.b32 %0, %1, %2, %3, 0xfe;" : "=r"(r) : "r"(a), "r"(b), "r"(c)); return r; }
__device__ __forceinline__ uint32_t diff2(uint32_t a, uint32_t b, uint32_t tag) { uint32_t r; asm("lop3.b32 %0, %1, %2, %3, 0x7e;" : "=r"(r) : "r"(a), "r"(b), "r"(tag)); return r; }
__device__ __forceinline__ float2 cmul(float2 a, float2 b) { return make_float2(a.x * b.x - a.y * b.y, a.x * b.y + a.y * b.x); }

template<int TB> __device__ __forceinline__ void wgmma_ss_160_0(float (&d)[96], uint32_t al, uint32_t ah, uint32_t bl, uint32_t bh) {
  asm volatile("{\n.reg .b64 da, db;\nmov.b64 da, {%80, %81};\nmov.b64 db, {%82, %83};\n"
    "wgmma.mma_async.sync.aligned.m64n160k16.f32.bf16.bf16 {%0,%1,%2,%3,%4,%5,%6,%7,%8,%9,%10,%11,%12,%13,%14,%15,%16,%17,%18,%19,%20,%21,%22,%23,%24,%25,%26,%27,%28,%29,%30,%31,%32,%33,%34,%35,%36,%37,%38,%39,%40,%41,%42,%43,%44,%45,%46,%47,%48,%49,%50,%51,%52,%53,%54,%55,%56,%57,%58,%59,%60,%61,%62,%63,%64,%65,%66,%67,%68,%69,%70,%71,%72,%73,%74,%75,%76,%77,%78,%79}, da, db, 1, 1, 1, 1, %84;\n}\n"
    : "+f"(d[0]),"+f"(d[1]),"+f"(d[2]),"+f"(d[3]),"+f"(d[4]),"+f"(d[5]),"+f"(d[6]),"+f"(d[7]),"+f"(d[8]),"+f"(d[9]),"+f"(d[10]),"+f"(d[11]),"+f"(d[12]),"+f"(d[13]),"+f"(d[14]),"+f"(d[15]),"+f"(d[16]),"+f"(d[17]),"+f"(d[18]),"+f"(d[19]),"+f"(d[20]),"+f"(d[21]),"+f"(d[22]),"+f"(d[23]),"+f"(d[24]),"+f"(d[25]),"+f"(d[26]),"+f"(d[27]),"+f"(d[28]),"+f"(d[29]),"+f"(d[30]),"+f"(d[31]),"+f"(d[32]),"+f"(d[33]),"+f"(d[34]),"+f"(d[35]),"+f"(d[36]),"+f"(d[37]),"+f"(d[38]),"+f"(d[39]),"+f"(d[40]),"+f"(d[41]),"+f"(d[42]),"+f"(d[43]),"+f"(d[44]),"+f"(d[45]),"+f"(d[46]),"+f"(d[47]),"+f"(d[48]),"+f"(d[49]),"+f"(d[50]),"+f"(d[51]),"+f"(d[52]),"+f"(d[53]),"+f"(d[54]),"+f"(d[55]),"+f"(d[56]),"+f"(d[57]),"+f"(d[58]),"+f"(d[59]),"+f"(d[60]),"+f"(d[61]),"+f"(d[62]),"+f"(d[63]),"+f"(d[64]),"+f"(d[65]),"+f"(d[66]),"+f"(d[67]),"+f"(d[68]),"+f"(d[69]),"+f"(d[70]),"+f"(d[71]),"+f"(d[72]),"+f"(d[73]),"+f"(d[74]),"+f"(d[75]),"+f"(d[76]),"+f"(d[77]),"+f"(d[78]),"+f"(d[79])
    : "r"(al), "r"(ah), "r"(bl), "r"(bh), "n"(TB));
}
template<int TB> __device__ __forceinline__ void wgmma_ss_144_0(float (&d)[96], uint32_t al, uint32_t ah, uint32_t bl, uint32_t bh) {
  asm volatile("{\n.reg .b64 da, db;\nmov.b64 da, {%72, %73};\nmov.b64 db, {%74, %75};\n"
    "wgmma.mma_async.sync.aligned.m64n144k16.f32.bf16.bf16 {%0,%1,%2,%3,%4,%5,%6,%7,%8,%9,%10,%11,%12,%13,%14,%15,%16,%17,%18,%19,%20,%21,%22,%23,%24,%25,%26,%27,%28,%29,%30,%31,%32,%33,%34,%35,%36,%37,%38,%39,%40,%41,%42,%43,%44,%45,%46,%47,%48,%49,%50,%51,%52,%53,%54,%55,%56,%57,%58,%59,%60,%61,%62,%63,%64,%65,%66,%67,%68,%69,%70,%71}, da, db, 1, 1, 1, 1, %76;\n}\n"
    : "+f"(d[0]),"+f"(d[1]),"+f"(d[2]),"+f"(d[3]),"+f"(d[4]),"+f"(d[5]),"+f"(d[6]),"+f"(d[7]),"+f"(d[8]),"+f"(d[9]),"+f"(d[10]),"+f"(d[11]),"+f"(d[12]),"+f"(d[13]),"+f"(d[14]),"+f"(d[15]),"+f"(d[16]),"+f"(d[17]),"+f"(d[18]),"+f"(d[19]),"+f"(d[20]),"+f"(d[21]),"+f"(d[22]),"+f"(d[23]),"+f"(d[24]),"+f"(d[25]),"+f"(d[26]),"+f"(d[27]),"+f"(d[28]),"+f"(d[29]),"+f"(d[30]),"+f"(d[31]),"+f"(d[32]),"+f"(d[33]),"+f"(d[34]),"+f"(d[35]),"+f"(d[36]),"+f"(d[37]),"+f"(d[38]),"+f"(d[39]),"+f"(d[40]),"+f"(d[41]),"+f"(d[42]),"+f"(d[43]),"+f"(d[44]),"+f"(d[45]),"+f"(d[46]),"+f"(d[47]),"+f"(d[48]),"+f"(d[49]),"+f"(d[50]),"+f"(d[51]),"+f"(d[52]),"+f"(d[53]),"+f"(d[54]),"+f"(d[55]),"+f"(d[56]),"+f"(d[57]),"+f"(d[58]),"+f"(d[59]),"+f"(d[60]),"+f"(d[61]),"+f"(d[62]),"+f"(d[63]),"+f"(d[64]),"+f"(d[65]),"+f"(d[66]),"+f"(d[67]),"+f"(d[68]),"+f"(d[69]),"+f"(d[70]),"+f"(d[71])
    : "r"(al), "r"(ah), "r"(bl), "r"(bh), "n"(TB));
}
template<int TB> __device__ __forceinline__ void wgmma_ss_96_0(float (&d)[96], uint32_t al, uint32_t ah, uint32_t bl, uint32_t bh) {
  asm volatile("{\n.reg .b64 da, db;\nmov.b64 da, {%48, %49};\nmov.b64 db, {%50, %51};\n"
    "wgmma.mma_async.sync.aligned.m64n96k16.f32.bf16.bf16 {%0,%1,%2,%3,%4,%5,%6,%7,%8,%9,%10,%11,%12,%13,%14,%15,%16,%17,%18,%19,%20,%21,%22,%23,%24,%25,%26,%27,%28,%29,%30,%31,%32,%33,%34,%35,%36,%37,%38,%39,%40,%41,%42,%43,%44,%45,%46,%47}, da, db, 1, 1, 1, 1, %52;\n}\n"
    : "+f"(d[0]),"+f"(d[1]),"+f"(d[2]),"+f"(d[3]),"+f"(d[4]),"+f"(d[5]),"+f"(d[6]),"+f"(d[7]),"+f"(d[8]),"+f"(d[9]),"+f"(d[10]),"+f"(d[11]),"+f"(d[12]),"+f"(d[13]),"+f"(d[14]),"+f"(d[15]),"+f"(d[16]),"+f"(d[17]),"+f"(d[18]),"+f"(d[19]),"+f"(d[20]),"+f"(d[21]),"+f"(d[22]),"+f"(d[23]),"+f"(d[24]),"+f"(d[25]),"+f"(d[26]),"+f"(d[27]),"+f"(d[28]),"+f"(d[29]),"+f"(d[30]),"+f"(d[31]),"+f"(d[32]),"+f"(d[33]),"+f"(d[34]),"+f"(d[35]),"+f"(d[36]),"+f"(d[37]),"+f"(d[38]),"+f"(d[39]),"+f"(d[40]),"+f"(d[41]),"+f"(d[42]),"+f"(d[43]),"+f"(d[44]),"+f"(d[45]),"+f"(d[46]),"+f"(d[47])
    : "r"(al), "r"(ah), "r"(bl), "r"(bh), "n"(TB));
}
template<int TB> __device__ __forceinline__ void wgmma_ss_96_48(float (&d)[96], uint32_t al, uint32_t ah, uint32_t bl, uint32_t bh) {
  asm volatile("{\n.reg .b64 da, db;\nmov.b64 da, {%48, %49};\nmov.b64 db, {%50, %51};\n"
    "wgmma.mma_async.sync.aligned.m64n96k16.f32.bf16.bf16 {%0,%1,%2,%3,%4,%5,%6,%7,%8,%9,%10,%11,%12,%13,%14,%15,%16,%17,%18,%19,%20,%21,%22,%23,%24,%25,%26,%27,%28,%29,%30,%31,%32,%33,%34,%35,%36,%37,%38,%39,%40,%41,%42,%43,%44,%45,%46,%47}, da, db, 1, 1, 1, 1, %52;\n}\n"
    : "+f"(d[48]),"+f"(d[49]),"+f"(d[50]),"+f"(d[51]),"+f"(d[52]),"+f"(d[53]),"+f"(d[54]),"+f"(d[55]),"+f"(d[56]),"+f"(d[57]),"+f"(d[58]),"+f"(d[59]),"+f"(d[60]),"+f"(d[61]),"+f"(d[62]),"+f"(d[63]),"+f"(d[64]),"+f"(d[65]),"+f"(d[66]),"+f"(d[67]),"+f"(d[68]),"+f"(d[69]),"+f"(d[70]),"+f"(d[71]),"+f"(d[72]),"+f"(d[73]),"+f"(d[74]),"+f"(d[75]),"+f"(d[76]),"+f"(d[77]),"+f"(d[78]),"+f"(d[79]),"+f"(d[80]),"+f"(d[81]),"+f"(d[82]),"+f"(d[83]),"+f"(d[84]),"+f"(d[85]),"+f"(d[86]),"+f"(d[87]),"+f"(d[88]),"+f"(d[89]),"+f"(d[90]),"+f"(d[91]),"+f"(d[92]),"+f"(d[93]),"+f"(d[94]),"+f"(d[95])
    : "r"(al), "r"(ah), "r"(bl), "r"(bh), "n"(TB));
}
__device__ __forceinline__ void wgmma_rs_72(float (&d)[36], uint32_t a0, uint32_t a1, uint32_t a2, uint32_t a3, uint32_t bl, uint32_t bh, int sd) {
  asm volatile("{\n.reg .pred p;\n.reg .b64 db;\nsetp.ne.b32 p, %42, 0;\nmov.b64 db, {%40, %41};\n"
    "wgmma.mma_async.sync.aligned.m64n72k16.f32.bf16.bf16 {%0,%1,%2,%3,%4,%5,%6,%7,%8,%9,%10,%11,%12,%13,%14,%15,%16,%17,%18,%19,%20,%21,%22,%23,%24,%25,%26,%27,%28,%29,%30,%31,%32,%33,%34,%35}, {%36,%37,%38,%39}, db, p, 1, 1, 1;\n}\n"
    : "+f"(d[0]),"+f"(d[1]),"+f"(d[2]),"+f"(d[3]),"+f"(d[4]),"+f"(d[5]),"+f"(d[6]),"+f"(d[7]),"+f"(d[8]),"+f"(d[9]),"+f"(d[10]),"+f"(d[11]),"+f"(d[12]),"+f"(d[13]),"+f"(d[14]),"+f"(d[15]),"+f"(d[16]),"+f"(d[17]),"+f"(d[18]),"+f"(d[19]),"+f"(d[20]),"+f"(d[21]),"+f"(d[22]),"+f"(d[23]),"+f"(d[24]),"+f"(d[25]),"+f"(d[26]),"+f"(d[27]),"+f"(d[28]),"+f"(d[29]),"+f"(d[30]),"+f"(d[31]),"+f"(d[32]),"+f"(d[33]),"+f"(d[34]),"+f"(d[35])
    : "r"(a0), "r"(a1), "r"(a2), "r"(a3), "r"(bl), "r"(bh), "r"(sd));
}
__device__ __forceinline__ void wgmma_rs_48(float (&d)[24], uint32_t a0, uint32_t a1, uint32_t a2, uint32_t a3, uint32_t bl, uint32_t bh, int sd) {
  asm volatile("{\n.reg .pred p;\n.reg .b64 db;\nsetp.ne.b32 p, %30, 0;\nmov.b64 db, {%28, %29};\n"
    "wgmma.mma_async.sync.aligned.m64n48k16.f32.bf16.bf16 {%0,%1,%2,%3,%4,%5,%6,%7,%8,%9,%10,%11,%12,%13,%14,%15,%16,%17,%18,%19,%20,%21,%22,%23}, {%24,%25,%26,%27}, db, p, 1, 1, 1;\n}\n"
    : "+f"(d[0]),"+f"(d[1]),"+f"(d[2]),"+f"(d[3]),"+f"(d[4]),"+f"(d[5]),"+f"(d[6]),"+f"(d[7]),"+f"(d[8]),"+f"(d[9]),"+f"(d[10]),"+f"(d[11]),"+f"(d[12]),"+f"(d[13]),"+f"(d[14]),"+f"(d[15]),"+f"(d[16]),"+f"(d[17]),"+f"(d[18]),"+f"(d[19]),"+f"(d[20]),"+f"(d[21]),"+f"(d[22]),"+f"(d[23])
    : "r"(a0), "r"(a1), "r"(a2), "r"(a3), "r"(bl), "r"(bh), "r"(sd));
}
template<int N,int OFF,int TB> __device__ __forceinline__ void wgmma_ss(float (&d)[96], uint32_t al, uint32_t ah, uint32_t bl, uint32_t bh) {
  if constexpr (N==160 && OFF==0) wgmma_ss_160_0<TB>(d, al, ah, bl, bh);
  else if constexpr (N==144 && OFF==0) wgmma_ss_144_0<TB>(d, al, ah, bl, bh);
  else if constexpr (N==96 && OFF==0) wgmma_ss_96_0<TB>(d, al, ah, bl, bh);
  else if constexpr (N==96 && OFF==48) wgmma_ss_96_48<TB>(d, al, ah, bl, bh);
}

__device__ __forceinline__ void dft3(float2& a, float2& b, float2& c) {
  const float s = 0.86602540378443864676f;
  float2 t = make_float2(b.x + c.x, b.y + c.y), d = make_float2(b.x - c.x, b.y - c.y);
  float2 m = make_float2(fmaf(-0.5f, t.x, a.x), fmaf(-0.5f, t.y, a.y));
  a = make_float2(a.x + t.x, a.y + t.y);
  b = make_float2(fmaf(s, d.y, m.x), fmaf(-s, d.x, m.y));
  c = make_float2(fmaf(-s, d.y, m.x), fmaf(s, d.x, m.y));
}
__device__ __forceinline__ void dft9(float2 (&x)[9]) {
  const float2 w1 = make_float2(0.76604444311897803520f, -0.64278760968653932632f);
  const float2 w2 = make_float2(0.17364817766693034885f, -0.98480775301220805937f);
  const float2 w4 = make_float2(-0.93969262078590838405f, -0.34202014332566873304f);
  dft3(x[0], x[3], x[6]); dft3(x[1], x[4], x[7]); dft3(x[2], x[5], x[8]);
  x[4] = cmul(x[4], w1); x[7] = cmul(x[7], w2); x[5] = cmul(x[5], w2); x[8] = cmul(x[8], w4);
  dft3(x[0], x[1], x[2]); dft3(x[3], x[4], x[5]); dft3(x[6], x[7], x[8]);
  float2 t;
  t = x[1]; x[1] = x[3]; x[3] = t;
  t = x[2]; x[2] = x[6]; x[6] = t;
  t = x[5]; x[5] = x[7]; x[7] = t;
}

__device__ __forceinline__ uint32_t* mod_ptr(Scratch* sc, int u, int t128) {
  const int i = t128 & 15;
  return u < 72 ? sc->moda + (t128 >> 4) * (2 * D_) + 16 * u + 2 * (i & 7) + (i >> 3) : sc->mod + 16 * (u - 72) + i;
}
__device__ __forceinline__ void mod_unit(Scratch* sc, int u, int t128, uint32_t sw_, uint32_t bar, int ph, uint32_t rb, uint32_t tag) {
  const int w = t128 >> 5, l = t128 & 31;
  uint32_t b[18];
#pragma unroll
  for (int i = 0; i < 18; i++) b[i] = lds(red + 512 + (72 * w + 4 * i + (l & 3)) * 4);
  const uint32_t sa = pin(sw_ + (144 * w + (l & 7) + 8 * (l >> 4)) * 32 + (((l >> 3) ^ (l >> 2)) & 1) * 16);
  const uint32_t sr = pin(rb + (l >> 2) * 16 + w * 4);
  uint32_t* const dst = pin(mod_ptr(sc, u, t128));
  const int kind = u / 36;
  const float mul = __uint_as_float(pin(__float_as_uint(kind == 0 ? 16.0f : 1.0f))), add = __uint_as_float(pin(__float_as_uint(kind == 1 || kind == 4 ? 1.0f : 0.0f)));
  mbar_wait(bar, ph);
  if (t128 == 0 && u < 72) TS(10);
  float d[3][4];
#pragma unroll
  for (int i = 0; i < 9; i++) {
    uint32_t a0, a1, a2, a3;
    asm volatile("ldmatrix.sync.aligned.m8n8.x4.trans.shared.b16 {%0,%1,%2,%3}, [%4];" : "=r"(a0), "=r"(a1), "=r"(a2), "=r"(a3) : "r"(sa + i * 512) : "memory");
    if (i < 3) mma16<false>(d[i], a0, a1, a2, a3, b[2 * i], b[2 * i + 1]);
    else mma16<true>(d[i % 3], a0, a1, a2, a3, b[2 * i], b[2 * i + 1]);
  }
  if ((l & 3) == 0) { sts(sr, __float_as_uint(d[0][0] + d[1][0] + d[2][0])); sts(sr + 128, __float_as_uint(d[0][2] + d[1][2] + d[2][2])); }
  bar_sync(4, 128);
  const uint4 v = lds4(rb + (l & 15) * 16);
  const float m = rbf(fmaf(rbf((__uint_as_float(v.x) + __uint_as_float(v.y)) + (__uint_as_float(v.z) + __uint_as_float(v.w))), mul, add));
  if (u < 72 || t128 < 16) *dst = __float_as_uint(m) | tag;
}

__device__ __forceinline__ float rsq(float x) { float r; asm("rsqrt.approx.ftz.f32 %0, %1;" : "=f"(r) : "f"(x)); return r; }
__device__ __forceinline__ void ln_stats2(const float (&a)[18], const float (&b)[18], float sc, float& oa, float& ra, float& ob, float& rb) {
  float v[4] = {0.f, 0.f, 0.f, 0.f}, w[4] = {0.f, 0.f, 0.f, 0.f};
#pragma unroll
  for (int i = 0; i < 18; i += 2) {
    v[0] += a[i]; v[1] = fmaf(a[i], a[i], v[1]); v[2] += b[i]; v[3] = fmaf(b[i], b[i], v[3]);
    w[0] += a[i + 1]; w[1] = fmaf(a[i + 1], a[i + 1], w[1]); w[2] += b[i + 1]; w[3] = fmaf(b[i + 1], b[i + 1], w[3]);
  }
#pragma unroll
  for (int e = 0; e < 4; e++) v[e] += w[e];
#pragma unroll
  for (int o = 16; o; o >>= 1) {
#pragma unroll
    for (int e = 0; e < 4; e++) v[e] += __shfl_xor_sync(0xffffffffu, v[e], o);
  }
  const float ma = v[0] * (1.0f / D_), mb = v[2] * (1.0f / D_);
  ra = sc * rsq(fmaxf(fmaf(-ma, ma, v[1] * (1.0f / D_)), 0.f) + 1e-5f);
  rb = sc * rsq(fmaxf(fmaf(-mb, mb, v[3] * (1.0f / D_)), 0.f) + 1e-5f);
  oa = -ma * ra; ob = -mb * rb;
}

__device__ __forceinline__ float tmat(int c, int q, int j) {
  const int ph = q == 1 ? 1024 * j : (q >> 1) * (c + 128 * j) + 512 * (q & 1);
  return __cosf((float)(((ph + 1024) & 2047) - 1024) * (6.283185307179586f / 2048.0f));
}
__device__ __forceinline__ uint32_t line_off(int k1, int kap, int pi, int f) {
  int kd = 64 * k1 + 9 * kap;
  if (kap == 0 && k1 > 4) kd -= 288;
  if (kd >= D_) kd -= D_;
  return pi * 2400 + ((min(kd, D_ - kd) ^ f) << 3);
}

constexpr int JSK = 5;
struct Ring { uint32_t st, ph; };
template <bool G2, class T> __device__ __forceinline__ void ring_next(T& st, T& ph) {
  if (++st == NST) st = 0;
  ph ^= ((G2 ? 0xDu : 0x1u) >> st) & 1;
}
__device__ __forceinline__ void arrive_if(uint32_t a, uint32_t p) {
  asm volatile("{\n.reg .pred p;\nsetp.ne.u32 p, %1, 0;\n@p mbarrier.arrive.shared::cta.b64 _, [%0];\n}" ::"r"(a), "r"(p) : "memory");
}
template <int NA> __device__ __forceinline__ void reg_fence_n(float (&d)[96]) {
#pragma unroll
  for (int i = 0; i < NA; i++) asm volatile("" : "+f"(d[i])::"memory");
}
template <int MODE>
__device__ __forceinline__ void gemm_main(float (&acc)[96], uint32_t da0, uint32_t da1, uint32_t db0, int wg, Ring& rg,
                                          bool rows, uint32_t* x1p, const uint32_t (&xr)[18]) {
  static_assert(JSK == NST - 1, "the held slot is the first one that is not refilled by GEMM1");
  constexpr int NKB = MODE == 3 ? 36 : 32, J = MODE == 3 ? J2 : JSK;
  constexpr uint32_t HA = 0x40000040u, HB = MODE == 3 ? 0x40000040u : 0x80000020u;
  constexpr uint32_t KA = 2048 >> 4, KB = MODE == 3 ? (32 >> 4) : (1024 >> 4);
  constexpr int NA = MODE == 3 ? 72 : MODE == 1 ? 96 : 80;
  const uint32_t t = threadIdx.x & 127;
  const uint32_t eb = full0 + 8 * NST;
  uint32_t pb = 0, rel = t == 0, prel = 0, ok = 0;
  int n = MODE == 3 ? NKB - J : X1K + 2 * wg;
#pragma unroll 1
  for (int pass = MODE == 3 ? 0 : -1;; pass++) {
#pragma unroll 1
    do {
      const uint32_t so = rg.st * ((MODE == 3 ? STAGE2 : STAGE) >> 4), cb = eb + 8 * rg.st;
      if (__builtin_expect(!ok, 0)) mbar_wait(full0 + 8 * rg.st, rg.ph);
      reg_fence_n<NA>(acc);
      if (MODE == 1 && wg) {
        wg_fence();
#pragma unroll
        for (int k = 0; k < 4; k++) wgmma_ss<96, 48, 1>(acc, da1 + so + k * KA, HA, db0 + so + k * KB, HB);
        wg_commit();
      }
      wg_fence();
#pragma unroll
      for (int k = 0; k < 4; k++) {
        if (k == 3) { ring_next<MODE == 3>(rg.st, rg.ph); ok = PEEK ? mbar_test(full0 + 8 * rg.st, rg.ph) : 0; }
        if (MODE == 0) wgmma_ss<160, 0, 1>(acc, da0 + so + k * KA, HA, db0 + so + k * KB, HB);
        else if (MODE == 3) wgmma_ss<144, 0, 0>(acc, da0 + so + k * KA, HA, db0 + so + k * KB, HB);
        else wgmma_ss<96, 0, 1>(acc, da0 + so + k * KA, HA, db0 + so + k * KB, HB);
      }
      wg_commit();
      wg_wait<1>();
      reg_fence_n<NA>(acc);
      arrive_if(pb, prel);
      pb = cb; prel = rel;
    } while (--n);
    if (pass == 2 - wg) break;
    if (MODE != 3 && pass < 0) {
      if (rows) {
#pragma unroll
        for (int i = 0; i < 9; i++) { x1p[32 * i] = xr[i]; x1p[128 * 288 + 32 * i] = xr[9 + i]; }
      }
      n = NKB - JSK - X1K - 2 * wg;
      continue;
    }
    n = 1;
    if (pass == 0) {
      if (MODE != 3) prel = rel & wg;
      else { rel = 0; if (J < NST) prel = 0; }
      n = J - 1 + wg;
      if (!wg) continue;
      wg_wait<0>();
      arrive_if(pb, prel);
      prel = 0;
    }
    bar_sync(1, 256);
  }
  wg_wait<0>();
  reg_fence_n<NA>(acc);
  if (MODE != 3) arrive_if(pb, MODE == 1 ? prel & ~wg : prel);
}

constexpr float GK1 = 2.0f * 0.7978845608028654f, GK3 = 8.0f * 0.044715f * 0.7978845608028654f;

__device__ __forceinline__ int kb2_order(int i) { const int wv = i / 6; return 6 * (i - 6 * wv) + ((0x431250 >> (4 * wv)) & 7); }

__device__ __forceinline__ int kb2_pos(int kb) { const int hf = kb >= 36, k = kb - 36 * hf, gr = k / 6; return 64 * hf + gr + 6 * ((0x154230 >> (4 * (k - 6 * gr))) & 7); }

__device__ __forceinline__ void wait_flags(const unsigned* p, int idx, unsigned target, uint32_t& ready) {
  int it = 0;
  while (!((ready >> idx) & 1) && it++ < SPIN_MAX) ready = __ballot_sync(0xffffffffu, (int)(ld_rlx(p) - target) >= 0);
}

enum { B_FULL = 0, B_EMPTY = 6, B_S4 = 12, B_S5, B_LAND, B_FLT = B_LAND + 6, B_Z1, B_Z2, B_GO, B_X, B_WM, B_NUM, B_W0 = B_NUM };

__global__ void __launch_bounds__(NTHR, 1)
fused_kernel(const Params p, const __grid_constant__ Maps maps) {
  extern __shared__ __align__(1024) uint8_t smem_raw[];
  const int bx = blockIdx.x, cta = bx < 112 || bx >= 130 ? bx : bx < 114 ? bx + 16 : bx - 2;
  const int tid = threadIdx.x, t128 = tid & 127;
  const int wp = __shfl_sync(0xffffffffu, tid >> 5, 0), wg = wp >> 2;
  const int l = tid & 31, g = l >> 2, t = l & 3;
  Scratch* const sc = p.s;
  const bool rows = cta < 128;
  const int mu = rows ? cta + 4 : cta - 128;
  const int R = mu - 12;

  uint32_t xr[18];
  uint32_t cv[3];
  const unsigned ep0 = ld_rlx(&sc->cnt[C_EP]);
  if (tid == 0) TS(0);
  if (wg == 2) {
#pragma unroll
    for (int i = 0; i < 3; i++) cv[i] = ld_nc(reinterpret_cast<const uint32_t*>(p.c) + min(t128 + 128 * i, 287));
    if (wp == 9 && l < 9 && rows) {
      const int h = 9 * cta + l;
      prefetch_l2(reinterpret_cast<const uint8_t*>(p.wmod) + (size_t)(h >> 1) * (12 * D_) + (h & 1) * (2 * D_), 2 * D_);
    }
    if (tid == 256 && mu < 72) {
      mbar_init(full0 + 8 * B_W0, 1);
      fence_async_smem();
      mbar_expect(full0 + 8 * B_W0, 18432);
#pragma unroll 1
      for (int i = 0; i < 3; i++) tma2d(sbase + O_P2 + i * 6144, &maps.wm, 16 * mu, 192 * i, full0 + 8 * B_W0);
    }
    __syncwarp();
#pragma unroll 1
    for (int u = mu < 72 ? mu : 72 + mu; u < 216; u += u < 72 ? 72 : NCTA) if (u < 72 || t128 < 16) *mod_ptr(sc, u, t128) = 0;
    if (wp == 11 && smem_u32(smem_raw) != sbase) __trap();
    if (wp >= 10 && elect()) {
#pragma unroll 1
      for (int i = wp - 10; i < B_NUM; i += 2) mbar_init(full0 + 8 * i, i == B_FLT ? 4 : i == B_WM ? 3 : i < B_LAND && i != B_S4 ? 2 : 1);
      fence_async_smem();
    }
    __syncwarp();
  } else if (rows) {
    const uint32_t* xs = reinterpret_cast<const uint32_t*>(p.x) + (size_t)(cta + 256 * wp) * 288 + l;
#pragma unroll
    for (int i = 0; i < 9; i++) { xr[i] = ld_nc(xs + 32 * i); xr[9 + i] = ld_nc(xs + 128 * 288 + 32 * i); }
  }
  CK(0);
  if (tid == 64 && cta == NCTA - 1) prefetch_l2(p.tab, sizeof(T_TAB));
  __syncwarp();
  auto tag_of = [](unsigned e) { return (e & 0x7fffu) | 0x8000u; };
  const int kap = 8 * ((wp & 3) ^ (wg & 1)) + g;
  uint32_t tb[4], sb1[3], lo[9];
#pragma unroll
  for (int i = 0; i < 4; i++) tb[i] = pin(pack_bf16(tmat(cta, 8 * (i >> 1) + g, 2 * t + 8 * (i & 1)), tmat(cta, 8 * (i >> 1) + g, 2 * t + 8 * (i & 1) + 1)));
#pragma unroll
  for (int i = 0; i < 3; i++) {
    const int d = 48 * wp + 16 * i + (l & 15);
    sb1[i] = pin(sbase + O_B1 + (l >> 4) * 9216 + (d % 9) * 1024 + (d & 63) * 16);
  }
#pragma unroll
  for (int k1 = 0; k1 < 9; k1++) lo[k1] = pin(sbase + O_Z1 + line_off(k1, kap, 4 * wg + t, cta & 3));
  const uint32_t snt = pin(sbase + O_NRM + ((l & 7) + 8 * (l >> 4)) * 1168 + (48 * wp + (l & 8)) * 2), sn = pin(sbase + O_NRM + wp * 2336 + l * 4);
  const uint32_t smask = pin(t ? 0u : 0xffff0000u);
  const uint32_t* const mp = pin(sc->moda + (cta >> 4) * (2 * D_) + 48 * wp + 2 * g);
  const uint4* const ftab = pin(p.tab + TB_F + (t128 ^ (wg << 5)));

  if (wg == 2) {
#pragma unroll
    for (int i = 0; i < 3; i++) {
      const float c0 = bf_lo(cv[i]), c1 = bf_hi(cv[i]);
      sts(red + 512 + min(t128 + 128 * i, 287) * 4, pack_bf16(__fdividef(c0, 1.0f + __expf(-c0)), __fdividef(c1, 1.0f + __expf(-c1))));
    }
    if (t128 == 0) sts(full0 + 248, ep0 + 1);
    if (wp == 9 && l < 11) asm volatile("prefetch.tensormap [%0];" ::"l"(&maps.z1 + l) : "memory");
    bar_sync(4, 128);
    if (mu < 72) {
      mod_unit(sc, mu, t128, sbase + O_P2, full0 + 8 * B_W0, 0, red, tag_of(upin(ep0) + 1));
      if (t128 == 0) TS(25);
    }
    CK(1);
  }
  const int pi = R / 15, col0 = 20 * (R - 15 * pi);
  const int xu = DF_ * pi + col0, xv = DF_ * (pi ? 16 - pi : 8) + col0;
  auto load_filter = [&](int a) {
    const int x = (a & 1) ? xv : xu;
    const bool wide = (x & 15) > 12;
    mbar_expect(full0 + 8 * B_FLT, wide ? 12288 : 8192);
    tma2d(sbase + O_RAW + a * 12288, &maps.wf[a & 2], x & ~15, 0, full0 + 8 * B_FLT);
    if (wide) tma2d(sbase + O_RAW + a * 12288 + 8192, &maps.wf[(a & 2) + 1], (x & ~15) + 32, 0, full0 + 8 * B_FLT);
  };
  uint4 af[4];
  if (rows) {
    uint2 ms[3], mc[3];
    auto load_mod = [&](uint32_t o = 0) {
#pragma unroll
      for (int i = 0; i < 3; i++) { ms[i] = ld_rlx2(mp + 2 * o + 16 * i); mc[i] = ld_rlx2(mp + 2 * o + D_ + 16 * i); }
    };
    if (wg < 2) {
      float a[18], b[18];
#pragma unroll
      for (int i = 0; i < 9; i++) { a[2 * i] = bf_lo(xr[i]); a[2 * i + 1] = bf_hi(xr[i]); b[2 * i] = bf_lo(xr[9 + i]); b[2 * i + 1] = bf_hi(xr[9 + i]); }
      float oa, ra, ob, rb;
      ln_stats2(a, b, 1.0f, oa, ra, ob, rb);
      CK(1);
      load_mod((__float_as_uint(ra) | __float_as_uint(rb)) >> 31);
#pragma unroll
      for (int i = 0; i < 9; i++) {
        sts(sn + i * 128, pack_bf16(fmaf(a[2 * i], ra, oa), fmaf(a[2 * i + 1], ra, oa)));
        sts(sn + 1168 + i * 128, pack_bf16(fmaf(b[2 * i], rb, ob), fmaf(b[2 * i + 1], rb, ob)));
      }
      CK(2);
      bar_arrive(10, NTHR);
#pragma unroll
      for (int kk = 0; kk < 4; kk++) af[kk] = ld_nc4(ftab + kk * 128);
      bar_sync(1, 256);
      if (tid == 0) TS(2);
    } else {
      bar_sync(10, NTHR);
      load_mod();
      CK(2);
      if (wp >= 10 && elect()) prefetch_l2(reinterpret_cast<const uint8_t*>(wp == 10 ? p.wr : p.wi) + cta * 9248, 9248);
      __syncwarp();
    }
    float rs[3][8];
#pragma unroll
    for (int i = 0; i < 3; i++) {
      uint32_t a0, a1, a2, a3;
      asm volatile("ldmatrix.sync.aligned.m8n8.x4.trans.shared.b16 {%0,%1,%2,%3}, [%4];" : "=r"(a0), "=r"(a1), "=r"(a2), "=r"(a3)
                   : "r"(snt + 32 * i) : "memory");
      mma16<false>(&rs[i][0], a0, a1, a2, a3, tb[0], tb[1]);
      mma16<false>(&rs[i][4], a0, a1, a2, a3, tb[2], tb[3]);
    }
    CK(3);
    const uint32_t tag16 = tag_of(upin(ep0) + 1), tag1 = tag16 & 1;
    {
      int it = 0;
#pragma unroll 1
      while (true) {
        uint32_t bad = 0;
#pragma unroll
        for (int i = 0; i < 3; i++) bad |= diff2(ms[i].x, ms[i].y, tag16) | diff2(mc[i].x, mc[i].y, tag16);
        if (!any(bad & 0xffffu) || ++it > SPIN_MAX) break;
        load_mod();
      }
      CK(4);
      if (tid == 0) TS(3);
#pragma unroll
      for (int i = 0; i < 3; i++) {
        const float c0 = bf_hi(mc[i].x), c1 = bf_hi(mc[i].y);
        const float s0 = __uint_as_float(ms[i].x & smask), s1 = __uint_as_float(ms[i].y & smask);
        stmatrix4(sb1[i], pack_bf16(fmaf(rs[i][0], c0, s0), rs[i][1] * c0), pack_bf16(fmaf(rs[i][2], c1, s1), rs[i][3] * c1),
                  pack_bf16(rs[i][4] * c0, rs[i][5] * c0), pack_bf16(rs[i][6] * c1, rs[i][7] * c1));
      }
    }
    fence_async_smem();
    CK(5);
    if (wg == 2) {
      bar_arrive(5, NTHR);
      if (R >= 0 && elect()) load_filter(wp - 8);
      __syncwarp();
      const int slot = 4 * (cta & 7) + ((cta >> 4) & 3) + 32 * (2 * (cta >> 6) + ((cta >> 3) & 1));
      const uint32_t c0 = upin(40 * slot), c1 = upin(60 * (wp & 1)), src = upin(sbase + O_Z1 + (wp & 1) * 9600);
      const CUtensorMap* mz = upin(&maps.z1);
      unsigned* hint = pin(sc->cnt + C_Z1 + 32 * (wp & 1));
      if (wp < 10) {
        bar_sync(2 + (wp & 1), 160);
        if (elect()) tma_st2d(mz, src, c0, c1);
        pause(HD1);
        if (elect()) red_add(hint, 1);
        bulk_commit_wait();
        if (tid == 256) TS(4);
        __syncwarp();
      }
    } else {
      bar_sync(5, NTHR);
      CK(6);
      float acc[36];
      const uint32_t db = (((sbase + O_B1 + wg * 9216) & 0x3FFFF) >> 4) | ((128 >> 4) << 16);
      wg_fence();
#pragma unroll
      for (int kk = 0; kk < 4; kk++) wgmma_rs_72(acc, af[kk].x, af[kk].y, af[kk].z, af[kk].w, db + kk * 16, 1024 >> 4, kk);
      wg_commit();
      wg_wait<0>();
      reg_fence(acc);
      CK(7);
      float2 za[9], zb[9];
#pragma unroll
      for (int i = 0; i < 9; i++) { za[i] = make_float2(acc[4 * i], acc[4 * i + 2]); zb[i] = make_float2(acc[4 * i + 1], acc[4 * i + 3]); }
      dft9(za); dft9(zb);
      if ((wp & 3) == wg) {
        const float sp = g ? 0.f : 1.f;
#pragma unroll
        for (int k = 1; k < 5; k++) {
          float2 a = za[k], b = za[9 - k];
          za[k] = make_float2(fmaf(sp, b.x, a.x), fmaf(-sp, b.y, a.y)); za[9 - k] = make_float2(fmaf(-sp, a.x, b.x), fmaf(sp, a.y, b.y));
          a = zb[k]; b = zb[9 - k];
          zb[k] = make_float2(fmaf(sp, b.x, a.x), fmaf(-sp, b.y, a.y)); zb[9 - k] = make_float2(fmaf(-sp, a.x, b.x), fmaf(sp, a.y, b.y));
        }
        const uint32_t w0 = set_tag(pack_bf16(za[0].y, 0.f), tag1), w1 = pack_bf16(zb[0].y, 0.f);
        asm volatile("{\n.reg .pred p;\nsetp.eq.u32 p, %3, 0;\n@p st.shared.v2.b32 [%0], {%1,%2};\n}" ::"r"(lo[0] + 288 * 8), "r"(w0), "r"(w1), "r"(g) : "memory");
        za[0].y = g ? za[0].y : 0.f; zb[0].y = g ? zb[0].y : 0.f;
      }
#pragma unroll
      for (int k1 = 0; k1 < 9; k1++) sts2(lo[k1], set_tag(pack_bf16(za[k1].x, za[k1].y), tag1), pack_bf16(zb[k1].x, zb[k1].y));
      fence_async_smem();
      CK(8);
      bar_arrive(2 + wg, 160);
      {
        const uint32_t fx = (((cta >> 4) ^ cta) & 3) << 3, dl = O_IN - O_Z1, st = sbase + O_ST + 15360 + tid * 16;
        sts4(st, (lo[0] ^ fx) + dl, (lo[1] ^ fx) + dl, (lo[2] ^ fx) + dl, (lo[3] ^ fx) + dl);
        sts4(st + 4096, (lo[4] ^ fx) + dl, (lo[5] ^ fx) + dl, (lo[6] ^ fx) + dl, (lo[7] ^ fx) + dl);
        sts4(st + 8192, (lo[8] ^ fx) + dl, (lo[0] ^ fx) + dl + (kap ? 0 : 288 * 8),
             sbase + O_B3 + wg * 1024 + (l >> 4) * 2048 + (2 * (kap & 24) + (l & 15)) * 16, 0);
      }
    }
    {
      uint32_t sy[6];
#pragma unroll
      for (int i = 0; i < 6; i++) {
        const int rr = 16 * (wp & 3) + g + 8 * (i & 1);
        sy[i] = sbase + O_Y + (t * 584 + 64 * ((3 * wg + (i >> 1) + 63 - rr) % 9) + rr) * 4;
      }
      sts4(sbase + O_ST + tid * 16, movm(tb[0]), movm(tb[2]), movm(tb[1]), movm(tb[3]));
      sts4(sbase + O_ST + 6144 + tid * 16, sy[0], sy[1], sy[2], sy[3]);
      sts2(sbase + O_ST + 12288 + tid * 8, sy[4], sy[5]);
    }
  } else {
    __syncthreads();
  }

  const unsigned ep = upin(lds(full0 + 248));
  const uint32_t tag16 = tag_of(ep), tag1 = ep & 1;
  auto load_wm = [&](int u) {
    if (wp > 8 && elect()) {
      mbar_expect(full0 + 8 * B_WM, 6144);
      tma2d(sbase + O_NRM + (wp - 9) * 6144, &maps.wm, 16 * u, 192 * (wp - 9), full0 + 8 * B_WM);
    }
    __syncwarp();
  };
  if (R >= 0) {
    const int nl = (col0 + wp < DF_) + (wg < 2 && col0 + wp + 12 < DF_);
    uint4 cf[2][4], G[4];
#pragma unroll
    for (int i = 0; i < 4; i++) {
      cf[0][i] = __ldg(p.tab + TB_P2 + i * 32 + l);
      cf[1][i] = __ldg(p.tab + TB_P2 + (pi ? i : 4 + i) * 32 + l);
      G[i] = __ldg(p.tab + TB_P2 + (8 + i) * 32 + l);
    }
    const uint32_t* zin = sc->z1 + (size_t)R * 5120;
    if (wp == 10) {
      const uint32_t* zu = upin(zin);
      if (elect()) mbar_expect(full0 + 8 * B_Z1, 20480);
      wait_cnt(sc->cnt + C_Z1 + 32 * (pi >> 2), 128 * ep - 40 * STRESS);
      if (elect()) {
        bulk_ld(sbase + O_P2, zu, 20480, full0 + 8 * B_Z1);
        TS(12);
      }
      __syncwarp();
    }
    mbar_wait(full0 + 8 * B_FLT, 0);
    CK(9);
    float wn[16], wc[16];
#pragma unroll 1
    for (int ln = nl - 1; ln >= 0; ln--) {
      const int col = col0 + wp + 12 * ln, k2 = (57 * col) & 63;
      const bool cj = k2 > 32;
      const float nr = ((col & 31) == 0 && col != 0 && col != 288 ? 0.5f : 1.0f) / ((float)S_ * D_), ni = cj ? -nr : nr;
#pragma unroll
      for (int i = 0; i < 16; i++) wn[i] = wc[i];
#pragma unroll
      for (int cl = 0; cl < 2; cl++) {
        const int v = cl ^ (cj && pi), e = ((v ? xv : xu) & 15) + wp + 12 * ln, sh = e < 32 ? 6 : 5;
        const uint32_t base = sbase + O_RAW + v * 12288 + (e < 32 ? 2 * e : 8192 - 64 + 2 * e), msk = e < 32 ? 0x30 : 0x10;
        const int dm = v ? (cj || pi ? -1 : 0) : 0;
#pragma unroll
        for (int tt = 0; tt < 4; tt++) {
          const int kc = g + 64 * (tt >> 1) + 16 * t + 8 * (tt & 1);
          uint32_t a = base + ((((cj ? -kc : kc) + dm) & 127) << sh);
          a ^= (a >> 3) & msk;
          wc[4 * tt + 2 * cl] = lds_bf(a) * nr; wc[4 * tt + 2 * cl + 1] = lds_bf(a + 24576) * ni;
        }
      }
    }
    const float al = __uint_as_float(pin((pi ? 0x3f800000u : 0u) + (l >> 5)));
    const uint32_t tagv = pin(tag1 + (l >> 5));
    CK(10);
    uint32_t off = pin(l * 160 + ((wp ^ (g & 3)) << 3));
    uint32_t offo = pin(sbase + O_P2 + 20480 + off - 64 * l), po = 3072;
    unsigned* hz2 = pin(sc->cnt + C_Z2);
    const uint32_t do2 = pin(12288 - 32 * l);
    const CUtensorMap* mz2 = upin(&maps.z2[wp == 0]);
    const uint32_t sz2 = upin(sbase + O_P2 + 20480 + (wp ? 0 : 12288)), cz2 = upin(40 * R + (wp ? 0 : 24));
    mbar_wait(full0 + 8 * B_Z1, 0);
    CK(11);
    if (tid == 0) TS(8);
    if (wg == 2) load_wm(72 + mu);
    uint2 v[4], v2[4];
    const uint32_t o2 = nl > 1 ? 96 : 0;
#pragma unroll
    for (int i = 0; i < 4; i++) { v[i] = lds2(sbase + O_P2 + off + i * 5120); v2[i] = lds2(sbase + O_P2 + off + o2 + i * 5120); }
    auto bad2 = [&]() {
      return any(or3(or3(diff2(v[0].x, v[1].x, tagv), diff2(v[2].x, v[3].x, tagv), diff2(v2[0].x, v2[1].x, tagv)), diff2(v2[2].x, v2[3].x, tagv), 0) & 1);
    };
    if (__builtin_expect(bad2() && nl, 0)) {
      FAILCNT(0);
      int it = 0;
      do {
#pragma unroll
        for (int i = 0; i < 4; i++) {
          v[i] = ld_rlx2(reinterpret_cast<const uint8_t*>(zin) + off + i * 5120);
          v2[i] = ld_rlx2(reinterpret_cast<const uint8_t*>(zin) + off + o2 + i * 5120);
        }
      } while (bad2() && ++it < SPIN_MAX);
    }
#pragma unroll 1
    for (int ln = 0; ln < nl; ln++, offo += do2, po = 2048) {
      float d[4][4];
      uint32_t A[8];
#pragma unroll
      for (int h = 0; h < 2; h++) {
        mma16<false>(d[2 * h], cf[0][0].x, cf[0][0].y, cf[0][0].z, cf[0][0].w, v[h].x, v[2 + h].x);
        mma16<false>(d[2 * h + 1], cf[1][0].x, cf[1][0].y, cf[1][0].z, cf[1][0].w, v[h].y, v[2 + h].y);
      }
      if (ln) { fence_async_smem(); bar_arrive(15, NTHR); }
#pragma unroll
      for (int h = 0; h < 2; h++)
#pragma unroll
        for (int L = 0; L < 2; L++) {
          const uint4 tw = cf[L][2 + h];
          const float* z = d[2 * h + L];
          const float2 z0 = cmul(make_float2(z[0], z[2]), make_float2(__uint_as_float(tw.x), __uint_as_float(tw.y)));
          const float2 z1 = cmul(make_float2(z[1], z[3]), make_float2(__uint_as_float(tw.z), __uint_as_float(tw.w)));
          A[4 * h + L] = pack_bf16(z0.x, z0.y); A[4 * h + 2 + L] = pack_bf16(z1.x, z1.y);
        }
#pragma unroll
      for (int tt = 0; tt < 4; tt++) {
        mma16<false>(d[tt], A[0], A[1], A[2], A[3], G[tt].x, G[tt].y);
        mma16<true>(d[tt], A[4], A[5], A[6], A[7], G[tt].z, G[tt].w);
      }
#pragma unroll
      for (int tt = 0; tt < 4; tt++) {
        const float ar = d[tt][0], aj = d[tt][1], br = d[tt][2], bj = d[tt][3];
        const float2 y1 = cmul(make_float2(fmaf(-al, bj, ar), fmaf(al, br, aj)), make_float2(wc[4 * tt], wc[4 * tt + 1]));
        const float2 y2 = cmul(make_float2(fmaf(al, ar, bj), fmaf(al, aj, -br)), make_float2(wc[4 * tt + 2], wc[4 * tt + 3]));
        A[2 * tt] = pack_bf16(fmaf(al, y2.x, y1.x), fmaf(-al, y2.y, -y1.y));
        A[2 * tt + 1] = pack_bf16(fmaf(al, y1.y, -y2.y), fmaf(al, y1.x, -y2.x));
      }
#pragma unroll
      for (int i = 0; i < 16; i++) wc[i] = wn[i];
#pragma unroll
      for (int i = 0; i < 4; i++) v[i] = v2[i];
#pragma unroll
      for (int tt = 0; tt < 4; tt++) {
        mma16<false>(d[tt], A[0], A[1], A[2], A[3], G[tt].x, G[tt].y);
        mma16<true>(d[tt], A[4], A[5], A[6], A[7], G[tt].z, G[tt].w);
      }
#pragma unroll
      for (int h = 0; h < 2; h++)
#pragma unroll
        for (int L = 0; L < 2; L++) {
          const uint4 tw = cf[L][2 + h];
          const float2 z0 = cmul(make_float2(d[2 * h][2 * L], d[2 * h][2 * L + 1]), make_float2(__uint_as_float(tw.x), __uint_as_float(tw.y)));
          const float2 z1 = cmul(make_float2(d[2 * h + 1][2 * L], d[2 * h + 1][2 * L + 1]), make_float2(__uint_as_float(tw.z), __uint_as_float(tw.w)));
          A[4 * h + 2 * L] = movm(pack_bf16(z0.x, z1.x)); A[4 * h + 2 * L + 1] = movm(pack_bf16(z0.y, z1.y));
        }
#pragma unroll
      for (int h = 0; h < 2; h++) {
        mma16<false>(d[0], cf[0][1].x, cf[0][1].y, cf[0][1].z, cf[0][1].w, A[4 * h], A[4 * h + 1]);
        mma16<false>(d[1], cf[1][1].x, cf[1][1].y, cf[1][1].z, cf[1][1].w, A[4 * h + 2], A[4 * h + 3]);
#pragma unroll
        for (int e = 0; e < 2; e++)
          sts2(offo + (2 * h + e) * po, set_tag(pack_bf16(d[0][e], d[0][2 + e]), tagv), pack_bf16(d[1][e], d[1][2 + e]));
      }
      CK(12 + ln);
    }
    if (tid == 0) TS(1);
    fence_async_smem();
    if (nl < 2 && wp != 8) bar_arrive(15, NTHR);
    if (wp) bar_arrive(6, NTHR);
    if (!(wp & 7)) {
      bar_sync(wp ? 15 : 6, NTHR);
      if (elect()) tma_st2d(mz2, sz2, cz2, 0);
      if (wp == 0 && elect()) red_add(hz2, 1);
      if (tid == 0) TS(9);
      if (wp == 0) bulk_commit_wait();
      __syncwarp();
    }
  }
  if (wg == 2) {
#pragma unroll 1
    for (int u = 72 + mu, k = 0; u < 216; u += NCTA, k ^= 1) {
      if (R < 0) { fence_async_smem(); bar_sync(4, 128); load_wm(u); }
      mod_unit(sc, u, t128, sbase + O_NRM, full0 + 8 * B_WM, k, red + 256 - 256 * k, tag16);
    }
    fence_async_smem();
    CK(13);
  }

  const int grp = bx / 11, m1 = bx - 11 * grp;
  const bool helper = (m1 & 3) == 3;
  const int f1 = 384 * grp + (helper ? 192 : 128) * (m1 >> 2);
  const int d1 = 160 * (m1 & 3), flip = m1 >= 7;
  const int a1bytes = helper ? 24576 : 16384;
  auto load_a1 = [&](int st, int kb) {
    mbar_expect(full0 + 8 * st, a1bytes);
    tma4d_ef(sbase + st * STAGE, helper ? &maps.w1b : &maps.w1a, 4 * (kb >> 3), 16 * (kb & 7), f1 >> 6, full0 + 8 * st);
  };

  if (rows) {
#pragma unroll
    for (int kk = 0; kk < 4; kk++) af[kk] = __ldg(p.tab + TB_E + kk * 128 + t128);
    const uint4 c0 = lds4(sbase + O_ST + tid * 16), c1 = lds4(sbase + O_ST + 6144 + tid * 16);
    const uint2 c2 = lds2(sbase + O_ST + 12288 + tid * 8);
    const uint32_t tc[4] = {c0.x, c0.y, c0.z, c0.w}, sy[6] = {c1.x, c1.y, c1.z, c1.w, c2.x, c2.y};
    const uint32_t l8 = pin(8 * l), syl = pin(sbase + O_Y + wp * 2336 + 8 * l);
    uint32_t sh3[3], ham[3];
#pragma unroll
    for (int k = 0; k < 3; k++) {
      const int pos = k && (l >> 4) == k - 1 ? (l & 8) + 4 * (l & 1) + ((l >> 1) & 3) : 4 * (l & 3) + ((l >> 2) & 3);
      const int sw = 2 * cta + (wp & 1), ph = pos ^ ((sw & 3) << 2);
      sh3[k] = pin((wp < 2 ? (l >> 4) * 4096 : sbase + O_B3 + (wp >> 1) * 4608 + (l >> 4) * 256) + (wp & 1) * 128 + ph * 4);
      const bool tg = ((ph ^ sw) & 7) == 0;
      ham[k] = pin(tg ? ~1u : ~0u);
    }
    unsigned* const hh3 = upin(sc->cnt + C_H3 + (cta >> 4));
    uint8_t* const h3g = upin(sc->h3 + (cta >> 4) * (18 * 4096) + (cta & 15) * 256);
    const int slot = 4 * (cta >> 4) + ((cta >> 1) & 3) + 32 * (2 * ((cta >> 3) & 1) + (cta & 1));
    const uint32_t* zin = sc->z2 + (size_t)slot * 4800;
    uint32_t ga[9];
    uint2 sh[9], sw[9];
    auto load_mod3 = [&](int part) {
#pragma unroll
      for (int i = 0; i < 9; i++) {
        if (part != 2) { const uint2 v = lds2(l8 + sbase + O_MOD + 256 * i); ga[i] = __byte_perm(v.x, v.y, 0x7632); }
        if (part != 1) { sh[i] = lds2(l8 + sbase + O_MOD + 4 * D_ + 256 * i); sw[i] = lds2(l8 + sbase + O_MOD + 8 * D_ + 256 * i); }
      }
    };
    if (wg == 2) {
      {
        uint4 v[4];
        const int i3 = min(t128 + 384, 431);
        int it = 0;
        while (true) {
          uint32_t bad = 0;
#pragma unroll
          for (int k = 0; k < 4; k++) v[k] = ld_rlx4(sc->mod + 4 * (k < 3 ? t128 + 128 * k : i3));
#pragma unroll
          for (int k = 0; k < 4; k++) {
            v[k].x ^= tag16; v[k].y ^= tag16; v[k].z ^= tag16; v[k].w ^= tag16;
            bad |= v[k].x | v[k].y | v[k].z | v[k].w;
          }
          if (!any(bad & 0xffffu) || ++it > SPIN_MAX) break;
        }
#pragma unroll
        for (int k = 0; k < 4; k++) sts4(sbase + O_MOD + 16 * (k < 3 ? t128 + 128 * k : i3), v[k].x, v[k].y, v[k].z, v[k].w);
      }
      CK(14);
      bulk_commit_wait();
      bar_sync(10, NTHR);
      mbar_wait(full0 + 8 * B_Z2, 0);
      if (elect()) {
        load_a1(wp - 8, wp - 8);
        if (wp > 8 && wp - 8 < NG1) prefetch_l2(reinterpret_cast<const uint8_t*>(p.w1) + (size_t)(128 * (4 * ((wp - 8) >> 1) + (cta >> 5)) + 64 * (wp & 1) + 2 * (cta & 31)) * (2 * F_), 4 * F_);
      }
      __syncwarp();
    } else {
      const uint4 e0 = lds4(sbase + O_ST + 15360 + tid * 16), e1 = lds4(sbase + O_ST + 19456 + tid * 16), e2 = lds4(sbase + O_ST + 23552 + tid * 16);
      const uint32_t li[9] = {e0.x, e0.y, e0.z, e0.w, e1.x, e1.y, e1.z, e1.w, e2.x}, lx = e2.y, sb3 = e2.z;
      if (MODPOS == 0) bar_arrive(10, NTHR);
      CK(14);
      if (wp == 1) {
        const uint32_t* zu = upin(zin);
        if (elect()) mbar_expect(full0 + 8 * B_Z2, 19200);
        wait_cnt(sc->cnt + C_Z2, 120 * ep - 40 * STRESS);
        if (elect()) {
          bulk_ld(sbase + O_IN, zu, 19200, full0 + 8 * B_Z2);
          TS(14);
        }
        __syncwarp();
      }
      if (MODPOS) { bar_sync(10, NTHR); load_mod3(MODPOS - 1); }
      mbar_wait(full0 + 8 * B_Z2, 0);
      CK(15);
      if (tid == 0) TS(11);
      uint2 v[10];
#pragma unroll
      for (int k1 = 0; k1 < 10; k1++) v[k1] = lds2(k1 < 9 ? li[k1] : lx);
      auto bad3 = [&]() {
        return any(or3(or3(diff2(v[0].x, v[1].x, tag1), diff2(v[2].x, v[3].x, tag1), diff2(v[4].x, v[5].x, tag1)), diff2(v[6].x, v[7].x, tag1), diff2(v[8].x, v[9].x, tag1)) & 1);
      };
      if (__builtin_expect(bad3(), 0)) {
        FAILCNT(1);
        int it = 0;
        do {
#pragma unroll
          for (int k1 = 0; k1 < 10; k1++) v[k1] = ld_rlx2(reinterpret_cast<const uint8_t*>(zin) + ((k1 < 9 ? li[k1] : lx) - (sbase + O_IN)));
        } while (bad3() && ++it < SPIN_MAX);
      }
      float2 za[9], zb[9];
#pragma unroll
      for (int i = 0; i < 9; i++) { za[i] = make_float2(bf_lo(v[i].x), bf_hi(v[i].x)); zb[i] = make_float2(bf_lo(v[i].y), bf_hi(v[i].y)); }
      if ((wp & 3) == wg) {
        const float sp = g ? 0.f : 1.f;
#pragma unroll
        for (int k = 1; k < 5; k++) {
          float2 a = za[k], b = za[9 - k];
          za[k] = make_float2(fmaf(-sp, b.x, a.x), fmaf(sp, b.y, a.y)); za[9 - k] = make_float2(fmaf(sp, a.x, b.x), fmaf(-sp, a.y, b.y));
          a = zb[k]; b = zb[9 - k];
          zb[k] = make_float2(fmaf(-sp, b.x, a.x), fmaf(sp, b.y, a.y)); zb[9 - k] = make_float2(fmaf(sp, a.x, b.x), fmaf(-sp, a.y, b.y));
        }
        za[0].y = g ? za[0].y : bf_lo(v[9].x); zb[0].y = g ? zb[0].y : bf_lo(v[9].y);
      }
      dft9(za); dft9(zb);
#pragma unroll
      for (int n = 0; n < 8; n += 2) {
        const int i0 = (9 - n) % 9, i1 = 8 - n;
        stmatrix4(sb3 + n * 2048, pack_bf16(za[i0].x, zb[i0].x), pack_bf16(za[i0].y, zb[i0].y), pack_bf16(za[i1].x, zb[i1].x), pack_bf16(za[i1].y, zb[i1].y));
      }
      stmatrix2(sb3 + 8 * 2048, pack_bf16(za[1].x, zb[1].x), pack_bf16(za[1].y, zb[1].y));
      fence_async_smem();
    }
    CK(16);
    __syncthreads();
    CK(17);
    float acc[24];
    const uint32_t db = (((sbase + O_B3 + wg * 6144) & 0x3FFFF) >> 4) | ((128 >> 4) << 16);
    wg_fence();
#pragma unroll
    for (int kk = 0; kk < 4; kk++) wgmma_rs_48(acc, af[kk].x, af[kk].y, af[kk].z, af[kk].w, db + kk * 16, 1024 >> 4, kk);
    wg_commit();
    if (wg < 2 && MODPOS == 0) load_mod3(0);
    wg_wait<0>();
    reg_fence(acc);
    CK(18);
#pragma unroll
    for (int i = 0; i < 3; i++) {
      const float* a = &acc[8 * i];
      const uint32_t a0 = pack_bf16(a[0], a[1]), a1 = pack_bf16(a[2], a[3]), a2 = pack_bf16(a[4], a[5]), a3 = pack_bf16(a[6], a[7]);
#pragma unroll
      for (int jh = 0; jh < 2; jh++) {
        float y[4];
        mma16<false>(y, a0, a1, a2, a3, tc[2 * jh], tc[2 * jh + 1]);
        sts(sy[2 * i] + jh * (4 * 584 * 4), pack_bf16(y[0], y[1]));
        sts(sy[2 * i + 1] + jh * (4 * 584 * 4), pack_bf16(y[2], y[3]));
      }
    }
    CK(19);
    if (wg == 2) { bar_arrive(7, NTHR); bar_sync(15, NB15); }
    else {
      bar_sync(7, NTHR);
      if ((LNM >> wp) & 1) bar_sync(15, NB15);
      CK(20);
      float a[18], b[18];
#pragma unroll
      for (int i = 0; i < 9; i++) {
        const uint2 y = lds2(syl + 256 * i);
        xr[i] = hfma2(ga[i], __byte_perm(y.x, y.y, 0x5410), xr[i]);
        xr[9 + i] = hfma2(ga[i], __byte_perm(y.x, y.y, 0x7632), xr[9 + i]);
        a[2 * i] = bf_lo(xr[i]); a[2 * i + 1] = bf_hi(xr[i]); b[2 * i] = bf_lo(xr[9 + i]); b[2 * i + 1] = bf_hi(xr[9 + i]);
      }
      float oa, ra, ob, rb;
      if (MODPOS == 2) load_mod3(2);
      ln_stats2(a, b, 1.0f, oa, ra, ob, rb);
      CK(21);
#pragma unroll
      for (int i = 0; i < 9; i++) {
        const float c0 = __uint_as_float(sw[i].x), c1 = __uint_as_float(sw[i].y), s0 = __uint_as_float(sh[i].x), s1 = __uint_as_float(sh[i].y);
        a[2 * i] = fmaf(fmaf(a[2 * i], ra, oa), c0, s0); a[2 * i + 1] = fmaf(fmaf(a[2 * i + 1], ra, oa), c1, s1);
        b[2 * i] = fmaf(fmaf(b[2 * i], rb, ob), c0, s0); b[2 * i + 1] = fmaf(fmaf(b[2 * i + 1], rb, ob), c1, s1);
      }
      ln_stats2(a, b, 0.5f, oa, ra, ob, rb);
      CK(22);
      if (wp < 2) bar_arrive(15, NB15);
      uint32_t hv[18];
#pragma unroll
      for (int i = 0; i < 9; i++) {
        const int k = i == 2 ? 1 : i == 6 ? 2 : 0;
        hv[2 * i] = bitsel(pack_bf16(fmaf(a[2 * i], ra, oa), fmaf(a[2 * i + 1], ra, oa)), ham[k], tag1);
        hv[2 * i + 1] = bitsel(pack_bf16(fmaf(b[2 * i], rb, ob), fmaf(b[2 * i + 1], rb, ob)), ham[k], tag1);
      }
      if (wp < 2) {
        if (elect()) red_add(hh3, 1);
#pragma unroll
        for (int i = 0; i < 18; i++) {
          const int k = (i >> 1) == 2 ? 1 : (i >> 1) == 6 ? 2 : 0;
          asm volatile("st.global.b32 [%0], %1;" ::"l"(h3g + sh3[k] + (i >> 1) * 8192 + (i & 1) * 64), "r"(hv[i]) : "memory");
        }
        if (tid == 0) TS(13);
      } else {
#pragma unroll
        for (int i = 0; i < 18; i++) sts(sh3[(i >> 1) == 2 ? 1 : (i >> 1) == 6 ? 2 : 0] + (i >> 1) * 512 + (i & 1) * 64, hv[i]);
        fence_async_smem();
      }
      bar_arrive(9, 288);
      CK(23);
    }
  }

  const bool g2 = rows;
  const int z2 = cta, r = z2 >> 6;
  const int s2 = 128 * ((z2 >> 2) & 15), d2 = 144 * (z2 & 3);
  constexpr int ST0 = (32 - JSK - 1) % NST, ST1 = 31 % NST;

  if (wg == 2) {
    asm volatile("setmaxnreg.dec.sync.aligned.u32 40;");
    auto load_b = [&](bool second, int i, int st) {
      const uint32_t lb = full0 + 8 * (B_LAND + st), bytes = second ? 18432 : STAGE - a1bytes;
      mbar_expect(lb, bytes);
      bulk_ld(sbase + (second ? st * STAGE2 + 16384 : st * STAGE + a1bytes),
              second ? sc->u + ((size_t)(36 * r + kb2_order(i)) * D_ + d2) * 128 : sc->h3 + ((size_t)(i * 18 + (d1 >> 5)) << 12), bytes, lb);
    };
    if (wp == 8) {
      int st = rows ? 4 : 0, ph = 1;
#pragma unroll 1
      for (int kb = st; kb < 32; kb++) {
        if (rows && (kb >> 1) == 2) mbar_wait(full0 + 8 * (B_S4 - 4 + kb), 0);
        mbar_wait(empty0 + 8 * st, ph);
        if (elect()) {
          load_a1(st, kb);
          if (kb >= PF2K && kb < PF2K + PF2 && g2)
            prefetch_l2(reinterpret_cast<const uint8_t*>(p.w2) + (size_t)(36 * r + kb2_order(kb - PF2K)) * 262144 + (z2 & 63) * 4096, 4096);
        }
        __syncwarp();
        ring_next<false>(st, ph);
      }
      if (g2) {
        st++;
#pragma unroll 1
        for (int i = 0; i < 36; i++) {
          if (i == HOLDA) mbar_wait(full0 + 8 * B_GO, 0);
          mbar_wait(empty0 + 8 * st, ph);
          if (elect()) {
            mbar_expect(full0 + 8 * st, 16384);
            tma3d_ef(sbase + st * STAGE2, &maps.w2, 64 * (36 * r + kb2_order(i)), s2 >> 6, full0 + 8 * st);
          }
          __syncwarp();
          ring_next<true>(st, ph);
        }
      }
    } else if (wp >= 10) {
      const int sw = wp - 10;
      if (sw) {
        if (rows) {
          bar_sync(9, 288);
          mbar_wait(full0 + 8 * H3W, 0);
          if (elect()) { tma_st3d(&maps.h3, sbase + O_B3 + 4608, 64 * (cta & 15), 18 * (cta >> 4), 1); mbar_arrive(full0 + 8 * B_S4); }
          bulk_commit_wait();
          if (elect()) {
            red_add(sc->cnt + C_H3 + (cta >> 4) + 8, 2);
            mbar_arrive(full0 + 8 * B_S5); mbar_arrive(full0 + 8 * B_S5);
            TS(24);
            asm volatile("fence.acq_rel.gpu;" ::: "memory");
            red_add(&sc->cnt[C_X + 64], 1);
          }
          __syncwarp();
        }
        if (g2) {
          uint2 v[3];
          int it = 0;
          do {
#pragma unroll
            for (int i = 0; i < 3; i++) v[i] = ld_rlx2(sc->mod + 3 * D_ + d2 + 2 * min(l + 32 * i, 71));
          } while (any(or3(diff2(v[0].x, v[0].y, tag16), diff2(v[1].x, v[1].y, tag16), diff2(v[2].x, v[2].y, tag16)) & 0xffffu) && ++it < SPIN_MAX);
#pragma unroll
          for (int i = 0; i < 3; i++) sts(sbase + O_GB + 4 * min(l + 32 * i, 71), __byte_perm(v[i].x, v[i].y, 0x7632));
          __syncwarp();
        }
        wait_cnt<true>(&sc->cnt[C_X + 64], 128 * ep);
        if (elect()) mbar_arrive(full0 + 8 * B_X);
        __syncwarp();
      }
      uint32_t lph = 0;
      auto check_tiles = [&](bool second, int n, int st, uint32_t o1, uint32_t d2nd) {
        const uint32_t b1 = pin(sbase + o1), b2 = pin(sbase + o1 + d2nd);
        int i = 0, it = 0;
#pragma unroll 1
        do {
          const uint32_t so = st * (second ? STAGE2 : STAGE);
          mbar_wait(full0 + 8 * (B_LAND + st), (lph >> st) & 1);
          lph ^= 1u << st;
          uint32_t v[20];
#pragma unroll
          for (int k = 0; k < 20; k++) if (!second || k < 10 || k >= 12) v[k] = lds(k < 12 ? b1 + so + k * 1024 : b2 + so + (k - 12) * 1024); else v[k] = tag1;
#pragma unroll
          for (int k = 0; k < 10; k++) v[k] = diff2(v[2 * k], v[2 * k + 1], tag1);
          const uint32_t bad = or3(or3(or3(v[0], v[1], v[2]), or3(v[3], v[4], v[5]), v[6]), v[7], or3(v[8], v[9], 0));
          if (__builtin_expect(any(bad & 1) && ++it < SPIN_MAX, 0)) {
            FAILCNT(2 + second);
            fence_async_smem();
            __syncwarp();
            if (elect()) load_b(second, i, st);
            __syncwarp();
            continue;
          }
          if (elect()) mbar_arrive(full0 + 8 * st);
          if (++st == NST) st = 0;
          i++;
        } while (i < n);
      };
      if (!sw) check_tiles(false, NV1, 0, a1bytes + l * 32 + (l >> 2) * 4, helper ? 4096 : 12288);
      const bool first = helper || m1 < W0N;
#pragma unroll 1
      for (int k = sw ? first : !first; k <= sw; k++) {
        const uint32_t stg = sbase + (!k ? ST0 * STAGE : helper ? ST1 * STAGE : O_U1);
        const int kbA = (f1 >> 6) + (helper ? 2 : 1) * (k ^ flip), kbB = helper ? (f1 >> 6) + 1 : kbA;
        uint8_t* const uA = upin(sc->u + ((size_t)kbA * D_ + d1) * 128);
        uint8_t* const uB = upin(sc->u + ((size_t)kbB * D_ + (helper ? d1 : d1 + 96)) * 128);
        unsigned* const fA = pin(sc->cnt + C_U + kb2_pos(kbA));
        unsigned* const fB = pin(sc->cnt + C_U + kb2_pos(kbB));
        const bool slow = sw && !helper;
        bar_sync(11 + k, 160);
        if (!slow) { if (elect()) { bulk_st(uA, stg, 96 * 128); TS(k ? 31 : 30); } __syncwarp(); }
        bar_sync(13 + k, 160);
        if (slow) {
          if (g2) mbar_wait(full0 + 8 * B_GO, 0);
          if (first) pause(10 * TRK0);
#pragma unroll 1
          for (int i = 0; i < 20480; i += 2048) {
            if (elect()) bulk_st(uA + i, stg + i, 2048);
            pause(k ? TRKC : TRK0);
          }
        }
        if (elect()) red_add(fA, 1);
        if ((helper ? k : !slow) && elect()) bulk_st(uB, stg + 96 * 128, helper ? 96 * 128 : 64 * 128);
        bulk_commit_wait();
        if (helper && k && elect()) red_add(fB, 1);
        if (elect()) {
          if (!k || helper) mbar_arrive(empty0 + 8 * (k ? ST1 : ST0));
          TS(k ? 23 : 17);
          mbar_arrive(full0 + 8 * B_S5);
        }
        __syncwarp();
      }
      if (sw) {
        mbar_wait(full0 + 8 * B_S5, rows);
        if (elect()) { asm volatile("fence.acq_rel.gpu;" ::: "memory"); red_add(&sc->cnt[C_X], 1); }
        __syncwarp();
      }
      if (g2) {
        if (!sw) check_tiles(true, NV2, 3, 16384 + l * 32 + (4 * (g & 1) + (g >> 1)) * 4, 10240);
        else {
          wait_cnt<true>(&sc->cnt[C_X], NCTA * ep);
          if (elect()) {
            mbar_arrive(full0 + 8 * B_X);
            if (cta == 0) sc->cnt[C_EP] = ep;
          }
          __syncwarp();
        }
      }
      __syncwarp();
    } else {
      uint32_t ready = 0;
      int st = 0, ph = 1;
#pragma unroll 1
      for (int kb = 0; kb < 32; kb++) {
        const uint8_t* src = upin(sc->h3 + ((size_t)(kb * 18 + (d1 >> 5)) << 12));
        const uint32_t dst = upin(sbase + st * STAGE + a1bytes), lb = full0 + 8 * ((kb < NV1 ? B_LAND : 0) + st);
        if (kb == NV1) { mbar_wait(full0 + 8 * B_X, 0); fence_async_glb(); ready = ~0u; }
        if (rows && (kb >> 1) == 2) mbar_wait(full0 + 8 * (B_S4 - 4 + kb), 0);
        mbar_wait(empty0 + 8 * st, ph);
        if (elect()) mbar_expect(lb, STAGE - a1bytes);
        wait_flags(sc->cnt + C_H3 + l, (kb & 7) + (kb < 8 ? 0 : 8), 32 * ep - 12 * STRESS, ready);
        if (elect()) bulk_ld(dst, src, STAGE - a1bytes, lb);
        ring_next<false>(st, ph);
      }
      if (g2) {
        ready = 0;
        st++;
#pragma unroll 1
        for (int i = 0; i < 36; i++) {
          const int kb = kb2_order(i);
          const uint8_t* src = upin(sc->u + ((size_t)(36 * r + kb) * D_ + d2) * 128);
          const uint32_t dst = upin(sbase + st * STAGE2 + 16384), lb = full0 + 8 * ((i < NV2 ? B_LAND : 0) + st);
          if (i == NV2) { mbar_wait(full0 + 8 * B_X, 1); fence_async_glb(); ready = ~0u; }
          mbar_wait(empty0 + 8 * st, ph);
          if (elect()) mbar_expect(lb, 18432);
          wait_flags(sc->cnt + C_U + 64 * r + l, i & 31, 4 * ep - 2 * STRESS, ready);
          if (elect()) {
            bulk_ld(dst, src, 18432, lb);
            if (i == GOAT) mbar_arrive(full0 + 8 * B_GO);
          }
          ring_next<true>(st, ph);
        }
      }
    }
  } else {
    asm volatile("setmaxnreg.inc.sync.aligned.u32 232;");
    const int wgu = wg;
    constexpr uint32_t sb4 = sbase >> 4;
    const int w = wp & 3;
    Ring rg = {0, 0};
    uint32_t* const x1p = p.out + (size_t)(cta + 256 * wp) * 288 + l;
    const uint32_t ad = pin(sbase + (!wg ? ST0 * STAGE : helper ? ST1 * STAGE : O_U1) + (8 * (l >> 4) + (l & 7)) * 128 + (((2 * w + ((l >> 3) & 1)) ^ (l & 7)) << 4));
    const uint32_t uam = pin(g == 2 * t ? 0xfffefffeu : ~0u), uom = tag1 * 0x10001u;
    float acc[96];
    constexpr uint32_t LA = (8192 >> 4) << 16, LB = (4096 >> 4) << 16;
    {
      const int fa = f1 + (helper ? 128 : 64) * (wg ^ flip) + 16 * w + g, fb = helper ? f1 + 64 + 16 * w + g : fa;
      const float a0 = 0.5f * __bfloat162float(p.b1[fa]), a1 = 0.5f * __bfloat162float(p.b1[fa + 8]);
      const float b0 = 0.5f * __bfloat162float(p.b1[fb]), b1 = 0.5f * __bfloat162float(p.b1[fb + 8]);
#pragma unroll
      for (int i = 0; i < 96; i++) acc[i] = i < 48 ? ((i & 2) ? a1 : a0) : ((i & 2) ? b1 : b0);
      reg_fence(acc);
    }
    if (!helper) gemm_main<0>(acc, sb4 + (wgu ^ flip) * 512 + LA, 0, sb4 + 1024 + LB, wgu, rg, rows, x1p, xr);
    else {
      float ac2[96];
#pragma unroll
      for (int i = 0; i < 96; i++) asm volatile("mov.b32 %0, %1;" : "=f"(ac2[i]) : "f"(acc[i]));
      gemm_main<1>(ac2, sb4 + (wgu ^ flip) * 1024 + LA, sb4 + 512 + LA, sb4 + 1536 + LB, wgu, rg, rows, x1p, xr);
#pragma unroll
      for (int i = 0; i < 96; i++) asm volatile("mov.b32 %0, %1;" : "=f"(acc[i]) : "f"(ac2[i]));
    }
    if (t128 == 0) { TS(wg ? 16 : 6); if (wg) TSC(5); }
    {
      float tp[2] = {0.f, 0.f};
#pragma unroll
      for (int j = 0; j < 12; j++) {
        const float* a = &acc[8 * j];
        const float k3 = j < 2 ? GK3 : fmaf(tp[j & 1], 0.0f, GK3);
        float o[8];
#pragma unroll
        for (int e = 0; e < 8; e++) {
          float z = a[e] * fmaf(a[e] * k3, a[e], GK1);
          asm("tanh.approx.f32 %0, %0;" : "+f"(z));
          if (e == GDEP) tp[j & 1] = z;
          o[e] = fmaf(a[e], z, a[e]);
        }
        stmatrix4t(ad + j * 2048, bitsel(pack_bf16(o[0], o[1]), uam, uom), pack_bf16(o[2], o[3]), bitsel(pack_bf16(o[4], o[5]), uam, uom), pack_bf16(o[6], o[7]));
        if (j == 5) {
          fence_async_smem();
          bar_arrive(11 + wgu, 160);
        }
        if ((j == 5 && helper && !wgu) || (j == 9 && !helper)) break;
      }
      fence_async_smem();
      bar_arrive(13 + wgu, 160);
      if (t128 == 0) TS(wg ? 29 : 28);
    }
    if (g2) {
      const int mb = wgu ^ r;
      const int odd = z2 & 1;
      uint4 gq[4];
      uint2 gs;
      {
        float a0 = 0.f, a1 = 0.f;
        if (wgu) { a0 = __bfloat162float(p.b2[s2 + 64 * mb + 16 * w + g]); a1 = __bfloat162float(p.b2[s2 + 64 * mb + 16 * w + 8 + g]); }
#pragma unroll
        for (int i = 0; i < 4; i++) gq[i] = lds4(sbase + O_GB + 32 * odd + 64 * i + 16 * t);
        gs = lds2(sbase + O_GB + (odd ? 0 : 256) + 8 * t);
#pragma unroll
        for (int i = 0; i < 72; i++) acc[i] = (i & 2) ? a1 : a0;
      }
      uint32_t* const ob = p.out + (size_t)(s2 + 64 * mb + 16 * w + g) * 288 + (d2 >> 1);
      uint32_t* const oq = pin(ob + 8 * odd + 4 * t);
      uint32_t* const os = pin(ob + (odd ? 0 : 64) + 2 * t);
      rg.st++;
      gemm_main<3>(acc, sb4 + mb * 512 + LA, 0, sb4 + 1024 + (1 << 16), wgu, rg, rows, x1p, xr);
      if (t128 == 0) { TS(wg ? 20 : 19); if (wg) TSC(22); }
      auto finish = [&](const float* aq, const float* as) {
#pragma unroll
        for (int i = 0; i < 8; i++) {
          const float* a = aq + 16 * (i >> 1) + 2 * (i & 1);
          const uint4 gv = gq[i >> 1];
          red_bf16x8(oq + (i & 1) * 2304 + 16 * (i >> 1), hmul2(gv.x, pack_bf16(a[0], a[1])), hmul2(gv.y, pack_bf16(a[4], a[5])),
                     hmul2(gv.z, pack_bf16(a[8], a[9])), hmul2(gv.w, pack_bf16(a[12], a[13])));
        }
#pragma unroll
        for (int i = 0; i < 2; i++) red_bf16x4(os + i * 2304, hmul2(gs.x, pack_bf16(as[2 * i], as[2 * i + 1])), hmul2(gs.y, pack_bf16(as[2 * i + 4], as[2 * i + 5])));
      };
      if (odd) finish(&acc[8], &acc[0]); else finish(&acc[0], &acc[64]);
      if (t128 == 0) TS(wg ? 7 : 21);
      __syncwarp();
    }
  }
}

typedef CUresult (*EncodeFn)(CUtensorMap*, CUtensorMapDataType, cuuint32_t, void*, const cuuint64_t*, const cuuint64_t*, const cuuint32_t*,
                             const cuuint32_t*, CUtensorMapInterleave, CUtensorMapSwizzle, CUtensorMapL2promotion, CUtensorMapFloatOOBfill);

struct Dim { cuuint64_t n, stride; cuuint32_t box; };
template <int RANK>
void make_map(EncodeFn enc, CUtensorMap* m, bool words, int swz, const void* ptr, const Dim (&d)[RANK]) {
  cuuint64_t gd[RANK], gs[RANK];
  cuuint32_t bx[RANK], es[RANK];
  for (int i = 0; i < RANK; i++) { gd[i] = d[i].n; gs[i] = d[i].stride; bx[i] = d[i].box; es[i] = 1; }
  enc(m, words ? CU_TENSOR_MAP_DATA_TYPE_UINT32 : CU_TENSOR_MAP_DATA_TYPE_BFLOAT16, RANK, const_cast<void*>(ptr), gd, gs + 1, bx, es,
      CU_TENSOR_MAP_INTERLEAVE_NONE, static_cast<CUtensorMapSwizzle>(swz),
      swz == 3 ? CU_TENSOR_MAP_L2_PROMOTION_L2_256B : CU_TENSOR_MAP_L2_PROMOTION_NONE, CU_TENSOR_MAP_FLOAT_OOB_FILL_NONE);
}

}

extern "C" void kernel_launch(void* const* d_in, const int* in_sizes, int n_in, void* d_out, int out_size) {
  (void)in_sizes; (void)n_in; (void)out_size;
  static EncodeFn enc = nullptr;
  static void *sptr = nullptr, *tptr = nullptr;
  if (!enc) {
    void* f = nullptr; cudaDriverEntryPointQueryResult qr;
    cudaGetDriverEntryPoint("cuTensorMapEncodeTiled", &f, cudaEnableDefault, &qr);
    enc = reinterpret_cast<EncodeFn>(f);
    cudaFuncSetAttribute(fused_kernel, cudaFuncAttributeMaxDynamicSharedMemorySize, SMEM_BYTES);
    cudaGetSymbolAddress(&sptr, g_s);
    cudaGetSymbolAddress(&tptr, T_TAB);
  }
  Params p;
  p.x = (const __nv_bfloat16*)d_in[0]; p.wr = (const __nv_bfloat16*)d_in[1]; p.wi = (const __nv_bfloat16*)d_in[2];
  p.b1 = (const __nv_bfloat16*)d_in[5]; p.b2 = (const __nv_bfloat16*)d_in[7];
  p.c = (const __nv_bfloat16*)d_in[8]; p.wmod = (const __nv_bfloat16*)d_in[9];
  p.w1 = (const __nv_bfloat16*)d_in[4]; p.w2 = (const __nv_bfloat16*)d_in[6];
  p.out = static_cast<uint32_t*>(d_out); p.s = static_cast<Scratch*>(sptr); p.tab = static_cast<const uint4*>(tptr);
  Maps maps;
  make_map<4>(enc, &maps.w1a, false, 3, p.w1, {{64, 0, 64}, {16, 128 * 2 * F_, 4}, {128, 2 * F_, 16}, {72, 128, 2}});
  make_map<4>(enc, &maps.w1b, false, 3, p.w1, {{64, 0, 64}, {16, 128 * 2 * F_, 4}, {128, 2 * F_, 16}, {72, 128, 3}});
  make_map<3>(enc, &maps.w2, false, 3, p.w2, {{64, 0, 64}, {F_, 2 * S_, 64}, {32, 128, 2}});
  make_map<2>(enc, &maps.z1, true, 0, p.s->z1, {{5120, 0, 40}, {120, 20480, 60}});
  for (int i = 0; i < 2; i++) make_map<2>(enc, &maps.z2[i], true, 0, p.s->z2, {{4800, 0, i ? 16u : 24u}, {128, 19200, 128}});
  for (int i = 0; i < 4; i++) make_map<2>(enc, &maps.wf[i], false, 2 - (i & 1), (i & 2) ? p.wi : p.wr, {{16 * DF_, 0, (i & 1) ? 16u : 32u}, {128, 32 * DF_, 128}});
  make_map<2>(enc, &maps.wm, false, 1, p.wmod, {{6 * D_, 0, 16}, {D_, 12 * D_, 192}});
  make_map<3>(enc, &maps.h3, true, 0, p.s->h3, {{1024, 0, 64}, {144, 4096, 18}, {4, 144 * 4096, 3}});
  fused_kernel<<<NCTA, NTHR, SMEM_BYTES, cudaStreamPerThread>>>(p, maps);
}
```

```cpp
#include <cuda_runtime.h>
#include <cuda_bf16.h>
#include <cuda.h>
#include <stdint.h>

namespace {

constexpr int S_ = 2048, D_ = 576, DF_ = 289, F_ = 4608;
constexpr int NCTA = 132, NTHR = 384;
constexpr int STAGE = 36864, NST = 6;
constexpr int STAGE2 = 34816, O_U1 = NST * STAGE2, O_GB = O_U1 + 20480, SMEM_BYTES = 232448;
constexpr uint32_t sbase = 1024, red = sbase + NST * STAGE, full0 = sbase + SMEM_BYTES - 256, empty0 = full0 + 8 * NST;
constexpr int O_NRM = 0, O_B1 = 19456, O_Z1 = 38912, O_P2 = 59392, O_ST = 3 * STAGE;
constexpr int O_RAW = 4 * STAGE;
constexpr int O_IN = 4 * STAGE, O_Y = O_IN + 19456, O_B3 = O_IN + 38912, O_MOD = O_IN + 57344;

__device__ __align__(128) const uint32_t T_TAB[5632] = {
0x3f803f80,0xbf803f80,0x3f803f80,0xbf803f80,0x3f803f80,0xbf803f80,0x3f803f80,0xbf803f80,0x3f803f80,0xbf803f80,0x3f803f80,0xbf803f80,
0x3f803f80,0xbf803f80,0x3f803f80,0xbf803f80,0x3f7f3f80,0xbdc90000,0x3f223f35,0xbf46bf35,0x3f753f7b,0xbe95be48,0x3ef13f0e,0xbf62bf55,
0x3f623f6d,0xbef1bec4,0x3e953ec4,0xbf75bf6d,0x3f463f55,0xbf22bf0e,0x3dc93e48,0xbf7fbf7b,0x3f7b3f80,0xbe480000,0xbe480000,0xbf7bbf80,
0x3f553f6d,0xbf0ebec4,0xbf0ebec4,0xbf55bf6d,0x3f0e3f35,0xbf55bf35,0xbf55bf35,0xbf0ebf35,0x3e483ec4,0xbf7bbf6d,0xbf7bbf6d,0xbe48bec4,
0x3f753f80,0xbe950000,0xbf62bf35,0xbef1bf35,0x3f223f55,0xbf46bf0e,0xbf7fbf7b,0x3dc9be48,0x3dc93ec4,0xbf7fbf6d,0xbf46bf6d,0x3f223ec4,
0xbef1be48,0xbf62bf7b,0xbe95bf0e,0x3f753f55,0x3f6d3f80,0xbec40000,0xbf6dbf80,0x3ec40000,0x3ec43f35,0xbf6dbf35,0xbec4bf35,0x3f6d3f35,
0xbec40000,0xbf6dbf80,0x3ec40000,0x3f6d3f80,0xbf6dbf35,0xbec4bf35,0x3f6d3f35,0x3ec43f35,0x3f623f80,0xbef10000,0xbe95bf35,0x3f753f35,
0x3dc93f0e,0xbf7fbf55,0x3f223e48,0x3f463f7b,0xbf46bec4,0xbf22bf6d,0x3f7f3f6d,0xbdc93ec4,0xbf75bf7b,0x3e95be48,0x3ef13f55,0xbf62bf0e,
0x3f553f80,0xbf0e0000,0x3f0e0000,0x3f553f80,0xbe483ec4,0xbf7bbf6d,0x3f7b3f6d,0xbe483ec4,0xbf7bbf35,0xbe48bf35,0x3e483f35,0xbf7bbf35,
0xbf0ebf6d,0x3f553ec4,0xbf55bec4,0xbf0ebf6d,0x3f463f80,0xbf220000,0x3f7f3f35,0x3dc93f35,0xbef13e48,0xbf62bf7b,0x3e953f55,0xbf75bf0e,
0xbf75bf6d,0x3e95bec4,0xbf62bec4,0xbef1bf6d,0x3dc9bf0e,0x3f7f3f55,0xbf22bf7b,0x3f463e48,0x3f353f80,0xbf350000,0x3f353f80,0xbf350000,
0xbf350000,0xbf35bf80,0xbf350000,0xbf35bf80,0xbf35bf80,0x3f350000,0xbf35bf80,0x3f350000,0x3f350000,0x3f353f80,0x3f350000,0x3f353f80,
0x3f223f80,0xbf460000,0xbdc93f35,0xbf7fbf35,0xbf62be48,0xbef1bf7b,0xbf75bf55,0x3e95bf0e,0xbe95bf6d,0x3f753ec4,0x3ef1bec4,0x3f623f6d,
0x3f7f3f0e,0x3dc93f55,0x3f463f7b,0xbf223e48,0x3f0e3f80,0xbf550000,0xbf550000,0xbf0ebf80,0xbf7bbec4,0xbe48bf6d,0xbe48bf6d,0x3f7b3ec4,
0x3e48bf35,0x3f7b3f35,0x3f7b3f35,0xbe483f35,0x3f553f6d,0xbf0e3ec4,0xbf0e3ec4,0xbf55bf6d,0x3ef13f80,0xbf620000,0xbf75bf35,0x3e95bf35,
0xbf7fbf0e,0x3dc9bf55,0x3f46be48,0x3f223f7b,0x3f22bec4,0x3f463f6d,0x3dc93f6d,0xbf7fbec4,0x3e953f7b,0xbf75be48,0xbf62bf55,0x3ef1bf0e,
0x3ec43f80,0xbf6d0000,0xbec4bf80,0x3f6d0000,0xbf6dbf35,0x3ec4bf35,0x3f6d3f35,0xbec43f35,0x3f6d0000,0x3ec43f80,0xbf6d0000,0xbec4bf80,
0xbec43f35,0xbf6dbf35,0x3ec4bf35,0x3f6d3f35,0x3e953f80,0xbf750000,0x3ef1bf35,0x3f623f35,0xbf46bf55,0x3f22bf0e,0x3dc93f7b,0xbf7fbe48,
0x3f7f3ec4,0xbdc93f6d,0xbf22bf6d,0x3f46bec4,0xbf623e48,0xbef1bf7b,0x3f753f0e,0xbe953f55,0x3e483f80,0xbf7b0000,0x3f7b0000,0x3e483f80,
0xbf0ebf6d,0x3f55bec4,0xbf553ec4,0xbf0ebf6d,0x3f553f35,0xbf0e3f35,0x3f0ebf35,0x3f553f35,0xbf7bbec4,0x3e48bf6d,0xbe483f6d,0xbf7bbec4,
0x3dc93f80,0xbf7f0000,0x3f463f35,0xbf223f35,0xbe95bf7b,0x3f75be48,0xbf62bf0e,0x3ef1bf55,0x3ef13f6d,0xbf623ec4,0x3f753ec4,0xbe953f6d,
0xbf22bf55,0x3f46bf0e,0xbf7fbe48,0x3dc9bf7b,0x3f80,0xbf800000,0x3f80,0xbf800000,0xbf80,0x3f800000,0xbf80,0x3f800000,
0x3f80,0xbf800000,0x3f80,0xbf800000,0xbf80,0x3f800000,0xbf80,0x3f800000,0xbdc93f80,0xbf7f0000,0xbf463f35,0xbf22bf35,
0x3e95bf7b,0x3f753e48,0x3f62bf0e,0x3ef13f55,0xbef13f6d,0xbf62bec4,0xbf753ec4,0xbe95bf6d,0x3f22bf55,0x3f463f0e,0x3f7fbe48,0x3dc93f7b,
0xbe483f80,0xbf7b0000,0xbf7b0000,0x3e48bf80,0x3f0ebf6d,0x3f553ec4,0x3f553ec4,0xbf0e3f6d,0xbf553f35,0xbf0ebf35,0xbf0ebf35,0x3f55bf35,
0x3f7bbec4,0x3e483f6d,0x3e483f6d,0xbf7b3ec4,0xbe953f80,0xbf750000,0xbef1bf35,0x3f62bf35,0x3f46bf55,0x3f223f0e,0xbdc93f7b,0xbf7f3e48,
0xbf7f3ec4,0xbdc9bf6d,0x3f22bf6d,0x3f463ec4,0x3f623e48,0xbef13f7b,0xbf753f0e,0xbe95bf55,0xbec43f80,0xbf6d0000,0x3ec4bf80,0x3f6d0000,
0x3f6dbf35,0x3ec43f35,0xbf6d3f35,0xbec4bf35,0xbf6d0000,0x3ec4bf80,0x3f6d0000,0xbec43f80,0x3ec43f35,0xbf6d3f35,0xbec4bf35,0x3f6dbf35,
0xbef13f80,0xbf620000,0x3f75bf35,0x3e953f35,0x3f7fbf0e,0x3dc93f55,0xbf46be48,0x3f22bf7b,0xbf22bec4,0x3f46bf6d,0xbdc93f6d,0xbf7f3ec4,
0xbe953f7b,0xbf753e48,0x3f62bf55,0x3ef13f0e,0xbf0e3f80,0xbf550000,0x3f550000,0xbf0e3f80,0x3f7bbec4,0xbe483f6d,0x3e48bf6d,0x3f7bbec4,
0xbe48bf35,0x3f7bbf35,0xbf7b3f35,0xbe48bf35,0xbf553f6d,0xbf0ebec4,0x3f0e3ec4,0xbf553f6d,0xbf223f80,0xbf460000,0x3dc93f35,0xbf7f3f35,
0x3f62be48,0xbef13f7b,0x3f75bf55,0x3e953f0e,0x3e95bf6d,0x3f75bec4,0xbef1bec4,0x3f62bf6d,0xbf7f3f0e,0x3dc9bf55,0xbf463f7b,0xbf22be48,
0xbf353f80,0xbf350000,0xbf353f80,0xbf350000,0x3f350000,0xbf353f80,0x3f350000,0xbf353f80,0x3f35bf80,0x3f350000,0x3f35bf80,0x3f350000,
0xbf350000,0x3f35bf80,0xbf350000,0x3f35bf80,0xbf463f80,0xbf220000,0xbf7f3f35,0x3dc9bf35,0x3ef13e48,0xbf623f7b,0xbe953f55,0xbf753f0e,
0x3f75bf6d,0x3e953ec4,0x3f62bec4,0xbef13f6d,0xbdc9bf0e,0x3f7fbf55,0x3f22bf7b,0x3f46be48,0xbf553f80,0xbf0e0000,0xbf0e0000,0x3f55bf80,
0x3e483ec4,0xbf7b3f6d,0xbf7b3f6d,0xbe48bec4,0x3f7bbf35,0xbe483f35,0xbe483f35,0xbf7b3f35,0x3f0ebf6d,0x3f55bec4,0x3f55bec4,0xbf0e3f6d,
0xbf623f80,0xbef10000,0x3e95bf35,0x3f75bf35,0xbdc93f0e,0xbf7f3f55,0xbf223e48,0x3f46bf7b,0x3f46bec4,0xbf223f6d,0xbf7f3f6d,0xbdc9bec4,
0x3f75bf7b,0x3e953e48,0xbef13f55,0xbf623f0e,0xbf6d3f80,0xbec40000,0x3f6dbf80,0x3ec40000,0xbec43f35,0xbf6d3f35,0x3ec4bf35,0x3f6dbf35,
0x3ec40000,0xbf6d3f80,0xbec40000,0x3f6dbf80,0x3f6dbf35,0xbec43f35,0xbf6d3f35,0x3ec4bf35,0xbf753f80,0xbe950000,0x3f62bf35,0xbef13f35,
0xbf223f55,0xbf463f0e,0x3f7fbf7b,0x3dc93e48,0xbdc93ec4,0xbf7f3f6d,0x3f46bf6d,0x3f22bec4,0x3ef1be48,0xbf623f7b,0x3e95bf0e,0x3f75bf55,
0xbf7b3f80,0xbe480000,0x3e480000,0xbf7b3f80,0xbf553f6d,0xbf0e3ec4,0x3f0ebec4,0xbf553f6d,0xbf0e3f35,0xbf553f35,0x3f55bf35,0xbf0e3f35,
0xbe483ec4,0xbf7b3f6d,0x3f7bbf6d,0xbe483ec4,0xbf7f3f80,0xbdc90000,0xbf223f35,0xbf463f35,0xbf753f7b,0xbe953e48,0xbef13f0e,0xbf623f55,
0xbf623f6d,0xbef13ec4,0xbe953ec4,0xbf753f6d,0xbf463f55,0xbf223f0e,0xbdc93e48,0xbf7f3f7b,0x3f803f80,0xbf803f80,0x3f803f80,0xbf803f80,
0x3f803f80,0xbf803f80,0x3f803f80,0xbf803f80,0x3f803f80,0xbf803f80,0x3f803f80,0xbf803f80,0x3f803f80,0xbf803f80,0x3f803f80,0xbf803f80,
0xbdc90000,0xbf7fbf80,0xbf46bf35,0xbf22bf35,0xbe95be48,0xbf75bf7b,0xbf62bf55,0xbef1bf0e,0xbef1bec4,0xbf62bf6d,0xbf75bf6d,0xbe95bec4,
0xbf22bf0e,0xbf46bf55,0xbf7fbf7b,0xbdc9be48,0xbf7bbf80,0x3e480000,0x3e480000,0x3f7b3f80,0xbf55bf6d,0x3f0e3ec4,0x3f0e3ec4,0x3f553f6d,
0xbf0ebf35,0x3f553f35,0x3f553f35,0x3f0e3f35,0xbe48bec4,0x3f7b3f6d,0x3f7b3f6d,0x3e483ec4,0x3e950000,0x3f753f80,0x3ef13f35,0xbf62bf35,
0x3f463f0e,0x3f223f55,0xbdc93e48,0xbf7fbf7b,0x3f7f3f6d,0x3dc93ec4,0xbf22bec4,0xbf46bf6d,0x3f623f7b,0xbef1be48,0xbf75bf55,0xbe95bf0e,
0x3f6d3f80,0xbec40000,0xbf6dbf80,0x3ec40000,0x3ec43f35,0xbf6dbf35,0xbec4bf35,0x3f6d3f35,0xbec40000,0xbf6dbf80,0x3ec40000,0x3f6d3f80,
0xbf6dbf35,0xbec4bf35,0x3f6d3f35,0x3ec43f35,0xbef10000,0xbf62bf80,0x3f753f35,0x3e953f35,0xbf7fbf55,0xbdc9bf0e,0x3f463f7b,0xbf22be48,
0xbf22bf6d,0x3f463ec4,0xbdc93ec4,0xbf7fbf6d,0x3e95be48,0x3f753f7b,0xbf62bf0e,0xbef1bf55,0xbf55bf80,0x3f0e0000,0xbf0e0000,0xbf55bf80,
0x3e48bec4,0x3f7b3f6d,0xbf7bbf6d,0x3e48bec4,0x3f7b3f35,0x3e483f35,0xbe48bf35,0x3f7b3f35,0x3f0e3f6d,0xbf55bec4,0x3f553ec4,0x3f0e3f6d,
0x3f220000,0x3f463f80,0xbdc9bf35,0x3f7f3f35,0x3f623f7b,0xbef13e48,0x3f753f0e,0x3e953f55,0xbe953ec4,0xbf75bf6d,0x3ef13f6d,0xbf62bec4,
0xbf7fbf55,0x3dc9bf0e,0xbf46be48,0xbf22bf7b,0x3f353f80,0xbf350000,0x3f353f80,0xbf350000,0xbf350000,0xbf35bf80,0xbf350000,0xbf35bf80,
0xbf35bf80,0x3f350000,0xbf35bf80,0x3f350000,0x3f350000,0x3f353f80,0x3f350000,0x3f353f80,0xbf460000,0xbf22bf80,0xbf7fbf35,0x3dc9bf35,
0xbef1bf7b,0x3f623e48,0x3e95bf0e,0x3f753f55,0x3f753ec4,0x3e953f6d,0x3f623f6d,0xbef13ec4,0x3dc93f55,0xbf7fbf0e,0xbf223e48,0xbf46bf7b,
0xbf0ebf80,0x3f550000,0x3f550000,0x3f0e3f80,0x3f7b3ec4,0x3e483f6d,0x3e483f6d,0xbf7bbec4,0xbe483f35,0xbf7bbf35,0xbf7bbf35,0x3e48bf35,
0xbf55bf6d,0x3f0ebec4,0x3f0ebec4,0x3f553f6d,0x3f620000,0x3ef13f80,0xbe953f35,0xbf75bf35,0xbdc93f55,0xbf7fbf0e,0xbf22bf7b,0x3f46be48,
0xbf46bf6d,0x3f22bec4,0x3f7f3ec4,0x3dc93f6d,0x3f753e48,0x3e953f7b,0xbef13f0e,0xbf62bf55,0x3ec43f80,0xbf6d0000,0xbec4bf80,0x3f6d0000,
0xbf6dbf35,0x3ec4bf35,0x3f6d3f35,0xbec43f35,0x3f6d0000,0x3ec43f80,0xbf6d0000,0xbec4bf80,0xbec43f35,0xbf6dbf35,0x3ec4bf35,0x3f6d3f35,
0xbf750000,0xbe95bf80,0x3f623f35,0xbef13f35,0x3f22bf0e,0x3f463f55,0xbf7fbe48,0xbdc9bf7b,0xbdc93f6d,0xbf7fbec4,0x3f46bec4,0x3f223f6d,
0xbef1bf7b,0x3f62be48,0xbe953f55,0xbf75bf0e,0xbe48bf80,0x3f7b0000,0xbf7b0000,0xbe48bf80,0x3f0e3f6d,0xbf553ec4,0x3f55bec4,0x3f0e3f6d,
0xbf55bf35,0x3f0ebf35,0xbf0e3f35,0xbf55bf35,0x3f7b3ec4,0xbe483f6d,0x3e48bf6d,0x3f7b3ec4,0x3f7f0000,0x3dc93f80,0x3f22bf35,0x3f463f35,
0xbf753e48,0xbe95bf7b,0xbef13f55,0xbf62bf0e,0x3f62bec4,0x3ef13f6d,0x3e95bf6d,0x3f753ec4,0xbf463f0e,0xbf22bf55,0xbdc93f7b,0xbf7fbe48,
0x3f80,0xbf800000,0x3f80,0xbf800000,0xbf80,0x3f800000,0xbf80,0x3f800000,0x3f80,0xbf800000,0x3f80,0xbf800000,
0xbf80,0x3f800000,0xbf80,0x3f800000,0xbf7f0000,0x3dc9bf80,0xbf22bf35,0x3f46bf35,0x3f753e48,0xbe953f7b,0x3ef13f55,0xbf623f0e,
0xbf62bec4,0x3ef1bf6d,0xbe95bf6d,0x3f75bec4,0x3f463f0e,0xbf223f55,0x3dc93f7b,0xbf7f3e48,0x3e48bf80,0x3f7b0000,0x3f7b0000,0xbe483f80,
0xbf0e3f6d,0xbf55bec4,0xbf55bec4,0x3f0ebf6d,0x3f55bf35,0x3f0e3f35,0x3f0e3f35,0xbf553f35,0xbf7b3ec4,0xbe48bf6d,0xbe48bf6d,0x3f7bbec4,
0x3f750000,0xbe953f80,0xbf623f35,0xbef1bf35,0xbf22bf0e,0x3f46bf55,0x3f7fbe48,0xbdc93f7b,0x3dc93f6d,0xbf7f3ec4,0xbf46bec4,0x3f22bf6d,
0x3ef1bf7b,0x3f623e48,0x3e953f55,0xbf753f0e,0xbec43f80,0xbf6d0000,0x3ec4bf80,0x3f6d0000,0x3f6dbf35,0x3ec43f35,0xbf6d3f35,0xbec4bf35,
0xbf6d0000,0x3ec4bf80,0x3f6d0000,0xbec43f80,0x3ec43f35,0xbf6d3f35,0xbec4bf35,0x3f6dbf35,0xbf620000,0x3ef1bf80,0x3e953f35,0xbf753f35,
0x3dc93f55,0xbf7f3f0e,0x3f22bf7b,0x3f463e48,0x3f46bf6d,0x3f223ec4,0xbf7f3ec4,0x3dc9bf6d,0xbf753e48,0x3e95bf7b,0x3ef13f0e,0xbf623f55,
0x3f0ebf80,0x3f550000,0xbf550000,0x3f0ebf80,0xbf7b3ec4,0x3e48bf6d,0xbe483f6d,0xbf7b3ec4,0x3e483f35,0xbf7b3f35,0x3f7bbf35,0x3e483f35,
0x3f55bf6d,0x3f0e3ec4,0xbf0ebec4,0x3f55bf6d,0x3f460000,0xbf223f80,0x3f7fbf35,0x3dc93f35,0x3ef1bf7b,0x3f62be48,0xbe95bf0e,0x3f75bf55,
0xbf753ec4,0x3e95bf6d,0xbf623f6d,0xbef1bec4,0xbdc93f55,0xbf7f3f0e,0x3f223e48,0xbf463f7b,0xbf353f80,0xbf350000,0xbf353f80,0xbf350000,
0x3f350000,0xbf353f80,0x3f350000,0xbf353f80,0x3f35bf80,0x3f350000,0x3f35bf80,0x3f350000,0xbf350000,0x3f35bf80,0xbf350000,0x3f35bf80,
0xbf220000,0x3f46bf80,0x3dc9bf35,0x3f7fbf35,0xbf623f7b,0xbef1be48,0xbf753f0e,0x3e95bf55,0x3e953ec4,0xbf753f6d,0xbef13f6d,0xbf623ec4,
0x3f7fbf55,0x3dc93f0e,0x3f46be48,0xbf223f7b,0x3f55bf80,0x3f0e0000,0x3f0e0000,0xbf553f80,0xbe48bec4,0x3f7bbf6d,0x3f7bbf6d,0x3e483ec4,
0xbf7b3f35,0x3e48bf35,0x3e48bf35,0x3f7bbf35,0xbf0e3f6d,0xbf553ec4,0xbf553ec4,0x3f0ebf6d,0x3ef10000,0xbf623f80,0xbf753f35,0x3e95bf35,
0x3f7fbf55,0xbdc93f0e,0xbf463f7b,0xbf223e48,0x3f22bf6d,0x3f46bec4,0x3dc93ec4,0xbf7f3f6d,0xbe95be48,0x3f75bf7b,0x3f62bf0e,0xbef13f55,
0xbf6d3f80,0xbec40000,0x3f6dbf80,0x3ec40000,0xbec43f35,0xbf6d3f35,0x3ec4bf35,0x3f6dbf35,0x3ec40000,0xbf6d3f80,0xbec40000,0x3f6dbf80,
0x3f6dbf35,0xbec43f35,0xbf6d3f35,0x3ec4bf35,0xbe950000,0x3f75bf80,0xbef13f35,0xbf623f35,0xbf463f0e,0x3f22bf55,0x3dc93e48,0xbf7f3f7b,
0xbf7f3f6d,0x3dc9bec4,0x3f22bec4,0xbf463f6d,0xbf623f7b,0xbef13e48,0x3f75bf55,0xbe953f0e,0x3f7bbf80,0x3e480000,0xbe480000,0x3f7bbf80,
0x3f55bf6d,0x3f0ebec4,0xbf0e3ec4,0x3f55bf6d,0x3f0ebf35,0x3f55bf35,0xbf553f35,0x3f0ebf35,0x3e48bec4,0x3f7bbf6d,0xbf7b3f6d,0x3e48bec4,
0x3dc90000,0xbf7f3f80,0x3f46bf35,0xbf223f35,0x3e95be48,0xbf753f7b,0x3f62bf55,0xbef13f0e,0x3ef1bec4,0xbf623f6d,0x3f75bf6d,0xbe953ec4,
0x3f22bf0e,0xbf463f55,0x3f7fbf7b,0xbdc93e48,0x3f803f80,0xbf803f80,0x3f803f80,0xbf803f80,0x3f803f80,0xbf803f80,0x3f803f80,0xbf803f80,
0x3f803f80,0xbf803f80,0x3f803f80,0xbf803f80,0x3f803f80,0xbf803f80,0x3f803f80,0xbf803f80,0xbf7fbf80,0x3dc90000,0xbf22bf35,0x3f463f35,
0xbf75bf7b,0x3e953e48,0xbef1bf0e,0x3f623f55,0xbf62bf6d,0x3ef13ec4,0xbe95bec4,0x3f753f6d,0xbf46bf55,0x3f223f0e,0xbdc9be48,0x3f7f3f7b,
0x3f7b3f80,0xbe480000,0xbe480000,0xbf7bbf80,0x3f553f6d,0xbf0ebec4,0xbf0ebec4,0xbf55bf6d,0x3f0e3f35,0xbf55bf35,0xbf55bf35,0xbf0ebf35,
0x3e483ec4,0xbf7bbf6d,0xbf7bbf6d,0xbe48bec4,0xbf75bf80,0x3e950000,0x3f623f35,0x3ef13f35,0xbf22bf55,0x3f463f0e,0x3f7f3f7b,0xbdc93e48,
0xbdc9bec4,0x3f7f3f6d,0x3f463f6d,0xbf22bec4,0x3ef13e48,0x3f623f7b,0x3e953f0e,0xbf75bf55,0x3f6d3f80,0xbec40000,0xbf6dbf80,0x3ec40000,
0x3ec43f35,0xbf6dbf35,0xbec4bf35,0x3f6d3f35,0xbec40000,0xbf6dbf80,0x3ec40000,0x3f6d3f80,0xbf6dbf35,0xbec4bf35,0x3f6d3f35,0x3ec43f35,
0xbf62bf80,0x3ef10000,0x3e953f35,0xbf75bf35,0xbdc9bf0e,0x3f7f3f55,0xbf22be48,0xbf46bf7b,0x3f463ec4,0x3f223f6d,0xbf7fbf6d,0x3dc9bec4,
0x3f753f7b,0xbe953e48,0xbef1bf55,0x3f623f0e,0x3f553f80,0xbf0e0000,0x3f0e0000,0x3f553f80,0xbe483ec4,0xbf7bbf6d,0x3f7b3f6d,0xbe483ec4,
0xbf7bbf35,0xbe48bf35,0x3e483f35,0xbf7bbf35,0xbf0ebf6d,0x3f553ec4,0xbf55bec4,0xbf0ebf6d,0xbf46bf80,0x3f220000,0xbf7fbf35,0xbdc9bf35,
0x3ef1be48,0x3f623f7b,0xbe95bf55,0x3f753f0e,0x3f753f6d,0xbe953ec4,0x3f623ec4,0x3ef13f6d,0xbdc93f0e,0xbf7fbf55,0x3f223f7b,0xbf46be48,
0x3f353f80,0xbf350000,0x3f353f80,0xbf350000,0xbf350000,0xbf35bf80,0xbf350000,0xbf35bf80,0xbf35bf80,0x3f350000,0xbf35bf80,0x3f350000,
0x3f350000,0x3f353f80,0x3f350000,0x3f353f80,0xbf22bf80,0x3f460000,0x3dc9bf35,0x3f7f3f35,0x3f623e48,0x3ef13f7b,0x3f753f55,0xbe953f0e,
0x3e953f6d,0xbf75bec4,0xbef13ec4,0xbf62bf6d,0xbf7fbf0e,0xbdc9bf55,0xbf46bf7b,0x3f22be48,0x3f0e3f80,0xbf550000,0xbf550000,0xbf0ebf80,
0xbf7bbec4,0xbe48bf6d,0xbe48bf6d,0x3f7b3ec4,0x3e48bf35,0x3f7b3f35,0x3f7b3f35,0xbe483f35,0x3f553f6d,0xbf0e3ec4,0xbf0e3ec4,0xbf55bf6d,
0xbef1bf80,0x3f620000,0x3f753f35,0xbe953f35,0x3f7f3f0e,0xbdc93f55,0xbf463e48,0xbf22bf7b,0xbf223ec4,0xbf46bf6d,0xbdc9bf6d,0x3f7f3ec4,
0xbe95bf7b,0x3f753e48,0x3f623f55,0xbef13f0e,0x3ec43f80,0xbf6d0000,0xbec4bf80,0x3f6d0000,0xbf6dbf35,0x3ec4bf35,0x3f6d3f35,0xbec43f35,
0x3f6d0000,0x3ec43f80,0xbf6d0000,0xbec4bf80,0xbec43f35,0xbf6dbf35,0x3ec4bf35,0x3f6d3f35,0xbe95bf80,0x3f750000,0xbef13f35,0xbf62bf35,
0x3f463f55,0xbf223f0e,0xbdc9bf7b,0x3f7f3e48,0xbf7fbec4,0x3dc9bf6d,0x3f223f6d,0xbf463ec4,0x3f62be48,0x3ef13f7b,0xbf75bf0e,0x3e95bf55,
0x3e483f80,0xbf7b0000,0x3f7b0000,0x3e483f80,0xbf0ebf6d,0x3f55bec4,0xbf553ec4,0xbf0ebf6d,0x3f553f35,0xbf0e3f35,0x3f0ebf35,0x3f553f35,
0xbf7bbec4,0x3e48bf6d,0xbe483f6d,0xbf7bbec4,0xbdc9bf80,0x3f7f0000,0xbf46bf35,0x3f22bf35,0x3e953f7b,0xbf753e48,0x3f623f0e,0xbef13f55,
0xbef1bf6d,0x3f62bec4,0xbf75bec4,0x3e95bf6d,0x3f223f55,0xbf463f0e,0x3f7f3e48,0xbdc93f7b,0x3f80,0xbf800000,0x3f80,0xbf800000,
0xbf80,0x3f800000,0xbf80,0x3f800000,0x3f80,0xbf800000,0x3f80,0xbf800000,0xbf80,0x3f800000,0xbf80,0x3f800000,
0x3dc9bf80,0x3f7f0000,0x3f46bf35,0x3f223f35,0xbe953f7b,0xbf75be48,0xbf623f0e,0xbef1bf55,0x3ef1bf6d,0x3f623ec4,0x3f75bec4,0x3e953f6d,
0xbf223f55,0xbf46bf0e,0xbf7f3e48,0xbdc9bf7b,0xbe483f80,0xbf7b0000,0xbf7b0000,0x3e48bf80,0x3f0ebf6d,0x3f553ec4,0x3f553ec4,0xbf0e3f6d,
0xbf553f35,0xbf0ebf35,0xbf0ebf35,0x3f55bf35,0x3f7bbec4,0x3e483f6d,0x3e483f6d,0xbf7b3ec4,0x3e95bf80,0x3f750000,0x3ef13f35,0xbf623f35,
0xbf463f55,0xbf22bf0e,0x3dc9bf7b,0x3f7fbe48,0x3f7fbec4,0x3dc93f6d,0xbf223f6d,0xbf46bec4,0xbf62be48,0x3ef1bf7b,0x3f75bf0e,0x3e953f55,
0xbec43f80,0xbf6d0000,0x3ec4bf80,0x3f6d0000,0x3f6dbf35,0x3ec43f35,0xbf6d3f35,0xbec4bf35,0xbf6d0000,0x3ec4bf80,0x3f6d0000,0xbec43f80,
0x3ec43f35,0xbf6d3f35,0xbec4bf35,0x3f6dbf35,0x3ef1bf80,0x3f620000,0xbf753f35,0xbe95bf35,0xbf7f3f0e,0xbdc9bf55,0x3f463e48,0xbf223f7b,
0x3f223ec4,0xbf463f6d,0x3dc9bf6d,0x3f7fbec4,0x3e95bf7b,0x3f75be48,0xbf623f55,0xbef1bf0e,0xbf0e3f80,0xbf550000,0x3f550000,0xbf0e3f80,
0x3f7bbec4,0xbe483f6d,0x3e48bf6d,0x3f7bbec4,0xbe48bf35,0x3f7bbf35,0xbf7b3f35,0xbe48bf35,0xbf553f6d,0xbf0ebec4,0x3f0e3ec4,0xbf553f6d,
0x3f22bf80,0x3f460000,0xbdc9bf35,0x3f7fbf35,0xbf623e48,0x3ef1bf7b,0xbf753f55,0xbe95bf0e,0xbe953f6d,0xbf753ec4,0x3ef13ec4,0xbf623f6d,
0x3f7fbf0e,0xbdc93f55,0x3f46bf7b,0x3f223e48,0xbf353f80,0xbf350000,0xbf353f80,0xbf350000,0x3f350000,0xbf353f80,0x3f350000,0xbf353f80,
0x3f35bf80,0x3f350000,0x3f35bf80,0x3f350000,0xbf350000,0x3f35bf80,0xbf350000,0x3f35bf80,0x3f46bf80,0x3f220000,0x3f7fbf35,0xbdc93f35,
0xbef1be48,0x3f62bf7b,0x3e95bf55,0x3f75bf0e,0xbf753f6d,0xbe95bec4,0xbf623ec4,0x3ef1bf6d,0x3dc93f0e,0xbf7f3f55,0xbf223f7b,0xbf463e48,
0xbf553f80,0xbf0e0000,0xbf0e0000,0x3f55bf80,0x3e483ec4,0xbf7b3f6d,0xbf7b3f6d,0xbe48bec4,0x3f7bbf35,0xbe483f35,0xbe483f35,0xbf7b3f35,
0x3f0ebf6d,0x3f55bec4,0x3f55bec4,0xbf0e3f6d,0x3f62bf80,0x3ef10000,0xbe953f35,0xbf753f35,0x3dc9bf0e,0x3f7fbf55,0x3f22be48,0xbf463f7b,
0xbf463ec4,0x3f22bf6d,0x3f7fbf6d,0x3dc93ec4,0xbf753f7b,0xbe95be48,0x3ef1bf55,0x3f62bf0e,0xbf6d3f80,0xbec40000,0x3f6dbf80,0x3ec40000,
0xbec43f35,0xbf6d3f35,0x3ec4bf35,0x3f6dbf35,0x3ec40000,0xbf6d3f80,0xbec40000,0x3f6dbf80,0x3f6dbf35,0xbec43f35,0xbf6d3f35,0x3ec4bf35,
0x3f75bf80,0x3e950000,0xbf623f35,0x3ef1bf35,0x3f22bf55,0x3f46bf0e,0xbf7f3f7b,0xbdc9be48,0x3dc9bec4,0x3f7fbf6d,0xbf463f6d,0xbf223ec4,
0xbef13e48,0x3f62bf7b,0xbe953f0e,0xbf753f55,0xbf7b3f80,0xbe480000,0x3e480000,0xbf7b3f80,0xbf553f6d,0xbf0e3ec4,0x3f0ebec4,0xbf553f6d,
0xbf0e3f35,0xbf553f35,0x3f55bf35,0xbf0e3f35,0xbe483ec4,0xbf7b3f6d,0x3f7bbf6d,0xbe483ec4,0x3f7fbf80,0x3dc90000,0x3f22bf35,0x3f46bf35,
0x3f75bf7b,0x3e95be48,0x3ef1bf0e,0x3f62bf55,0x3f62bf6d,0x3ef1bec4,0x3e95bec4,0x3f75bf6d,0x3f46bf55,0x3f22bf0e,0x3dc9be48,0x3f7fbf7b,
0x3f803f80,0xbf803f80,0x3f803f80,0xbf803f80,0x3f803f80,0xbf803f80,0x3f803f80,0xbf803f80,0x3f803f80,0xbf803f80,0x3f803f80,0xbf803f80,
0x3f803f80,0xbf803f80,0x3f803f80,0xbf803f80,0x3dc90000,0x3f7f3f80,0x3f463f35,0x3f223f35,0x3e953e48,0x3f753f7b,0x3f623f55,0x3ef13f0e,
0x3ef13ec4,0x3f623f6d,0x3f753f6d,0x3e953ec4,0x3f223f0e,0x3f463f55,0x3f7f3f7b,0x3dc93e48,0xbf7bbf80,0x3e480000,0x3e480000,0x3f7b3f80,
0xbf55bf6d,0x3f0e3ec4,0x3f0e3ec4,0x3f553f6d,0xbf0ebf35,0x3f553f35,0x3f553f35,0x3f0e3f35,0xbe48bec4,0x3f7b3f6d,0x3f7b3f6d,0x3e483ec4,
0xbe950000,0xbf75bf80,0xbef1bf35,0x3f623f35,0xbf46bf0e,0xbf22bf55,0x3dc9be48,0x3f7f3f7b,0xbf7fbf6d,0xbdc9bec4,0x3f223ec4,0x3f463f6d,
0xbf62bf7b,0x3ef13e48,0x3f753f55,0x3e953f0e,0x3f6d3f80,0xbec40000,0xbf6dbf80,0x3ec40000,0x3ec43f35,0xbf6dbf35,0xbec4bf35,0x3f6d3f35,
0xbec40000,0xbf6dbf80,0x3ec40000,0x3f6d3f80,0xbf6dbf35,0xbec4bf35,0x3f6d3f35,0x3ec43f35,0x3ef10000,0x3f623f80,0xbf75bf35,0xbe95bf35,
0x3f7f3f55,0x3dc93f0e,0xbf46bf7b,0x3f223e48,0x3f223f6d,0xbf46bec4,0x3dc9bec4,0x3f7f3f6d,0xbe953e48,0xbf75bf7b,0x3f623f0e,0x3ef13f55,
0xbf55bf80,0x3f0e0000,0xbf0e0000,0xbf55bf80,0x3e48bec4,0x3f7b3f6d,0xbf7bbf6d,0x3e48bec4,0x3f7b3f35,0x3e483f35,0xbe48bf35,0x3f7b3f35,
0x3f0e3f6d,0xbf55bec4,0x3f553ec4,0x3f0e3f6d,0xbf220000,0xbf46bf80,0x3dc93f35,0xbf7fbf35,0xbf62bf7b,0x3ef1be48,0xbf75bf0e,0xbe95bf55,
0x3e95bec4,0x3f753f6d,0xbef1bf6d,0x3f623ec4,0x3f7f3f55,0xbdc93f0e,0x3f463e48,0x3f223f7b,0x3f353f80,0xbf350000,0x3f353f80,0xbf350000,
0xbf350000,0xbf35bf80,0xbf350000,0xbf35bf80,0xbf35bf80,0x3f350000,0xbf35bf80,0x3f350000,0x3f350000,0x3f353f80,0x3f350000,0x3f353f80,
0x3f460000,0x3f223f80,0x3f7f3f35,0xbdc93f35,0x3ef13f7b,0xbf62be48,0xbe953f0e,0xbf75bf55,0xbf75bec4,0xbe95bf6d,0xbf62bf6d,0x3ef1bec4,
0xbdc9bf55,0x3f7f3f0e,0x3f22be48,0x3f463f7b,0xbf0ebf80,0x3f550000,0x3f550000,0x3f0e3f80,0x3f7b3ec4,0x3e483f6d,0x3e483f6d,0xbf7bbec4,
0xbe483f35,0xbf7bbf35,0xbf7bbf35,0x3e48bf35,0xbf55bf6d,0x3f0ebec4,0x3f0ebec4,0x3f553f6d,0xbf620000,0xbef1bf80,0x3e95bf35,0x3f753f35,
0x3dc9bf55,0x3f7f3f0e,0x3f223f7b,0xbf463e48,0x3f463f6d,0xbf223ec4,0xbf7fbec4,0xbdc9bf6d,0xbf75be48,0xbe95bf7b,0x3ef1bf0e,0x3f623f55,
0x3ec43f80,0xbf6d0000,0xbec4bf80,0x3f6d0000,0xbf6dbf35,0x3ec4bf35,0x3f6d3f35,0xbec43f35,0x3f6d0000,0x3ec43f80,0xbf6d0000,0xbec4bf80,
0xbec43f35,0xbf6dbf35,0x3ec4bf35,0x3f6d3f35,0x3f750000,0x3e953f80,0xbf62bf35,0x3ef1bf35,0xbf223f0e,0xbf46bf55,0x3f7f3e48,0x3dc93f7b,
0x3dc9bf6d,0x3f7f3ec4,0xbf463ec4,0xbf22bf6d,0x3ef13f7b,0xbf623e48,0x3e95bf55,0x3f753f0e,0xbe48bf80,0x3f7b0000,0xbf7b0000,0xbe48bf80,
0x3f0e3f6d,0xbf553ec4,0x3f55bec4,0x3f0e3f6d,0xbf55bf35,0x3f0ebf35,0xbf0e3f35,0xbf55bf35,0x3f7b3ec4,0xbe483f6d,0x3e48bf6d,0x3f7b3ec4,
0xbf7f0000,0xbdc9bf80,0xbf223f35,0xbf46bf35,0x3f75be48,0x3e953f7b,0x3ef1bf55,0x3f623f0e,0xbf623ec4,0xbef1bf6d,0xbe953f6d,0xbf75bec4,
0x3f46bf0e,0x3f223f55,0x3dc9bf7b,0x3f7f3e48,0x3f80,0xbf800000,0x3f80,0xbf800000,0xbf80,0x3f800000,0xbf80,0x3f800000,
0x3f80,0xbf800000,0x3f80,0xbf800000,0xbf80,0x3f800000,0xbf80,0x3f800000,0x3f7f0000,0xbdc93f80,0x3f223f35,0xbf463f35,
0xbf75be48,0x3e95bf7b,0xbef1bf55,0x3f62bf0e,0x3f623ec4,0xbef13f6d,0x3e953f6d,0xbf753ec4,0xbf46bf0e,0x3f22bf55,0xbdc9bf7b,0x3f7fbe48,
0x3e48bf80,0x3f7b0000,0x3f7b0000,0xbe483f80,0xbf0e3f6d,0xbf55bec4,0xbf55bec4,0x3f0ebf6d,0x3f55bf35,0x3f0e3f35,0x3f0e3f35,0xbf553f35,
0xbf7b3ec4,0xbe48bf6d,0xbe48bf6d,0x3f7bbec4,0xbf750000,0x3e95bf80,0x3f62bf35,0x3ef13f35,0x3f223f0e,0xbf463f55,0xbf7f3e48,0x3dc9bf7b,
0xbdc9bf6d,0x3f7fbec4,0x3f463ec4,0xbf223f6d,0xbef13f7b,0xbf62be48,0xbe95bf55,0x3f75bf0e,0xbec43f80,0xbf6d0000,0x3ec4bf80,0x3f6d0000,
0x3f6dbf35,0x3ec43f35,0xbf6d3f35,0xbec4bf35,0xbf6d0000,0x3ec4bf80,0x3f6d0000,0xbec43f80,0x3ec43f35,0xbf6d3f35,0xbec4bf35,0x3f6dbf35,
0x3f620000,0xbef13f80,0xbe95bf35,0x3f75bf35,0xbdc9bf55,0x3f7fbf0e,0xbf223f7b,0xbf46be48,0xbf463f6d,0xbf22bec4,0x3f7fbec4,0xbdc93f6d,
0x3f75be48,0xbe953f7b,0xbef1bf0e,0x3f62bf55,0x3f0ebf80,0x3f550000,0xbf550000,0x3f0ebf80,0xbf7b3ec4,0x3e48bf6d,0xbe483f6d,0xbf7b3ec4,
0x3e483f35,0xbf7b3f35,0x3f7bbf35,0x3e483f35,0x3f55bf6d,0x3f0e3ec4,0xbf0ebec4,0x3f55bf6d,0xbf460000,0x3f22bf80,0xbf7f3f35,0xbdc9bf35,
0xbef13f7b,0xbf623e48,0x3e953f0e,0xbf753f55,0x3f75bec4,0xbe953f6d,0x3f62bf6d,0x3ef13ec4,0x3dc9bf55,0x3f7fbf0e,0xbf22be48,0x3f46bf7b,
0xbf353f80,0xbf350000,0xbf353f80,0xbf350000,0x3f350000,0xbf353f80,0x3f350000,0xbf353f80,0x3f35bf80,0x3f350000,0x3f35bf80,0x3f350000,
0xbf350000,0x3f35bf80,0xbf350000,0x3f35bf80,0x3f220000,0xbf463f80,0xbdc93f35,0xbf7f3f35,0x3f62bf7b,0x3ef13e48,0x3f75bf0e,0xbe953f55,
0xbe95bec4,0x3f75bf6d,0x3ef1bf6d,0x3f62bec4,0xbf7f3f55,0xbdc9bf0e,0xbf463e48,0x3f22bf7b,0x3f55bf80,0x3f0e0000,0x3f0e0000,0xbf553f80,
0xbe48bec4,0x3f7bbf6d,0x3f7bbf6d,0x3e483ec4,0xbf7b3f35,0x3e48bf35,0x3e48bf35,0x3f7bbf35,0xbf0e3f6d,0xbf553ec4,0xbf553ec4,0x3f0ebf6d,
0xbef10000,0x3f62bf80,0x3f75bf35,0xbe953f35,0xbf7f3f55,0x3dc9bf0e,0x3f46bf7b,0x3f22be48,0xbf223f6d,0xbf463ec4,0xbdc9bec4,0x3f7fbf6d,
0x3e953e48,0xbf753f7b,0xbf623f0e,0x3ef1bf55,0xbf6d3f80,0xbec40000,0x3f6dbf80,0x3ec40000,0xbec43f35,0xbf6d3f35,0x3ec4bf35,0x3f6dbf35,
0x3ec40000,0xbf6d3f80,0xbec40000,0x3f6dbf80,0x3f6dbf35,0xbec43f35,0xbf6d3f35,0x3ec4bf35,0x3e950000,0xbf753f80,0x3ef1bf35,0x3f62bf35,
0x3f46bf0e,0xbf223f55,0xbdc9be48,0x3f7fbf7b,0x3f7fbf6d,0xbdc93ec4,0xbf223ec4,0x3f46bf6d,0x3f62bf7b,0x3ef1be48,0xbf753f55,0x3e95bf0e,
0x3f7bbf80,0x3e480000,0xbe480000,0x3f7bbf80,0x3f55bf6d,0x3f0ebec4,0xbf0e3ec4,0x3f55bf6d,0x3f0ebf35,0x3f55bf35,0xbf553f35,0x3f0ebf35,
0x3e48bec4,0x3f7bbf6d,0xbf7b3f6d,0x3e48bec4,0xbdc90000,0x3f7fbf80,0xbf463f35,0x3f22bf35,0xbe953e48,0x3f75bf7b,0xbf623f55,0x3ef1bf0e,
0xbef13ec4,0x3f62bf6d,0xbf753f6d,0x3e95bec4,0xbf223f0e,0x3f46bf55,0xbf7f3f7b,0x3dc9be48,0x40003f80,0x3fb53f80,0x3f80,0xbfb53f80,
0x40004000,0xbfb50000,0x0,0xbfb5c000,0x40004000,0xbfb5c000,0x0,0x3fb50000,0x40004000,0x3fb50000,0x0,0x3fb54000,
0x3fff3f80,0x3fa23f80,0xbe49bf80,0xbfc6bf80,0x3ff53ffb,0xbfe2bec8,0xbf15bec8,0xbf71bffb,0x3fe23fed,0xbf15bfed,0xbf71bf44,0x3ff53f44,
0x3fc63fd5,0x3fff3f8e,0xbfa2bf8e,0x3e493fd5,0x3ffb3f80,0x3f8e3f80,0xbec83f80,0xbfd53f80,0x3fd53fed,0xbffbbf44,0xbf8ebf44,0xbec8bfed,
0x3f8e3fb5,0x3ec8bfb5,0xbfd5bfb5,0x3ffb3fb5,0x3ec83f44,0x3fd53fed,0xbffbbfed,0xbf8e3f44,0x3ff53f80,0x3f713f80,0xbf15bf80,0xbfe2bf80,
0x3fa23fd5,0xbfffbf8e,0xbfc6bf8e,0x3e49bfd5,0x3e493f44,0x3fa2bf44,0xbfffbfed,0x3fc63fed,0xbf71bec8,0x3f153ffb,0xbfe2bffb,0xbff5bec8,
0x3fed3f80,0x3f443f80,0xbf443f80,0xbfed3f80,0x3f443fb5,0xbfedbfb5,0xbfedbfb5,0x3f44bfb5,0xbf440000,0x3fed0000,0xbfedc000,0x3f444000,
0xbfedbfb5,0xbf443fb5,0xbf44bfb5,0xbfedbfb5,0x3fe23f80,0x3f153f80,0xbf71bf80,0xbff5bf80,0x3e493f8e,0xbfc6bfd5,0xbfffbfd5,0x3fa2bf8e,
0xbfc6bf44,0x3fff3f44,0xbfa2bfed,0xbe493fed,0xbff5bffb,0xbfe23ec8,0x3f15bec8,0xbf71bffb,0x3fd53f80,0x3ec83f80,0xbf8e3f80,0xbffb3f80,
0xbec83f44,0xbf8ebfed,0xbffbbfed,0x3fd5bf44,0xbffbbfb5,0x3fd53fb5,0xbec8bfb5,0xbf8e3fb5,0xbf8ebfed,0xbffbbf44,0x3fd53f44,0x3ec8bfed,
0x3fc63f80,0x3e493f80,0xbfa2bf80,0xbfffbf80,0xbf713ec8,0xbf15bffb,0xbfe2bffb,0x3ff5bec8,0xbff5bfed,0x3f713fed,0x3f15bf44,0xbfe23f44,
0x3e49bf8e,0xbfa2bfd5,0x3fff3fd5,0x3fc6bf8e,0x3f80,0xbfb53f80,0xc0003f80,0xbfb53f80,0xc000,0x3fb50000,0x40000000,0xbfb54000,
0x4000,0x3fb5c000,0xc0000000,0x3fb50000,0xc000,0xbfb50000,0x40000000,0x3fb5c000,0xbe493f80,0xbfc63f80,0xbfffbf80,0xbfa2bf80,
0x3f15bffb,0x3f713ec8,0x3ff53ec8,0xbfe23ffb,0xbf713fed,0x3ff5bfed,0xbfe2bf44,0x3f153f44,0x3fa2bfd5,0xbe49bf8e,0x3fc63f8e,0x3fffbfd5,
0xbec83f80,0xbfd53f80,0xbffb3f80,0xbf8e3f80,0x3f8ebfed,0x3ec83f44,0x3fd53f44,0xbffb3fed,0xbfd53fb5,0x3ffbbfb5,0xbf8ebfb5,0xbec83fb5,
0x3ffbbf44,0x3f8ebfed,0x3ec83fed,0x3fd5bf44,0xbf153f80,0xbfe23f80,0xbff5bf80,0xbf71bf80,0x3fc6bfd5,0xbe493f8e,0x3fa23f8e,0xbfff3fd5,
0xbfff3f44,0x3fc6bf44,0xbe49bfed,0xbfa23fed,0x3fe23ec8,0x3ff5bffb,0xbf713ffb,0x3f153ec8,0xbf443f80,0xbfed3f80,0xbfed3f80,0xbf443f80,
0x3fedbfb5,0xbf443fb5,0x3f443fb5,0xbfed3fb5,0xbfed0000,0x3f440000,0x3f44c000,0xbfed4000,0x3f443fb5,0x3fedbfb5,0xbfed3fb5,0xbf443fb5,
0xbf713f80,0xbff53f80,0xbfe2bf80,0xbf15bf80,0x3fffbf8e,0xbfa23fd5,0x3e493fd5,0xbfc63f8e,0xbfa2bf44,0xbe493f44,0x3fc6bfed,0xbfff3fed,
0xbf153ffb,0x3f71bec8,0xbff53ec8,0xbfe23ffb,0xbf8e3f80,0xbffb3f80,0xbfd53f80,0xbec83f80,0x3ffbbf44,0xbfd53fed,0xbec83fed,0xbf8e3f44,
0xbec8bfb5,0xbf8e3fb5,0x3ffbbfb5,0xbfd53fb5,0xbfd53fed,0xbec83f44,0xbf8ebf44,0xbffb3fed,0xbfa23f80,0xbfff3f80,0xbfc6bf80,0xbe49bf80,
0x3fe2bec8,0xbff53ffb,0xbf713ffb,0xbf153ec8,0x3f15bfed,0xbfe23fed,0x3ff5bf44,0xbf713f44,0xbfff3f8e,0xbfc63fd5,0x3e49bfd5,0xbfa23f8e,
0xc0003f80,0xbfb53f80,0x3f80,0x3fb53f80,0xc0004000,0x3fb50000,0x0,0x3fb5c000,0xc0004000,0x3fb5c000,0x0,0xbfb50000,
0xc0004000,0xbfb50000,0x0,0xbfb54000,0xbfff3f80,0xbfa23f80,0x3e49bf80,0x3fc6bf80,0xbff53ffb,0x3fe2bec8,0x3f15bec8,0x3f71bffb,
0xbfe23fed,0x3f15bfed,0x3f71bf44,0xbff53f44,0xbfc63fd5,0xbfff3f8e,0x3fa2bf8e,0xbe493fd5,0xbffb3f80,0xbf8e3f80,0x3ec83f80,0x3fd53f80,
0xbfd53fed,0x3ffbbf44,0x3f8ebf44,0x3ec8bfed,0xbf8e3fb5,0xbec8bfb5,0x3fd5bfb5,0xbffb3fb5,0xbec83f44,0xbfd53fed,0x3ffbbfed,0x3f8e3f44,
0xbff53f80,0xbf713f80,0x3f15bf80,0x3fe2bf80,0xbfa23fd5,0x3fffbf8e,0x3fc6bf8e,0xbe49bfd5,0xbe493f44,0xbfa2bf44,0x3fffbfed,0xbfc63fed,
0x3f71bec8,0xbf153ffb,0x3fe2bffb,0x3ff5bec8,0xbfed3f80,0xbf443f80,0x3f443f80,0x3fed3f80,0xbf443fb5,0x3fedbfb5,0x3fedbfb5,0xbf44bfb5,
0x3f440000,0xbfed0000,0x3fedc000,0xbf444000,0x3fedbfb5,0x3f443fb5,0x3f44bfb5,0x3fedbfb5,0xbfe23f80,0xbf153f80,0x3f71bf80,0x3ff5bf80,
0xbe493f8e,0x3fc6bfd5,0x3fffbfd5,0xbfa2bf8e,0x3fc6bf44,0xbfff3f44,0x3fa2bfed,0x3e493fed,0x3ff5bffb,0x3fe23ec8,0xbf15bec8,0x3f71bffb,
0xbfd53f80,0xbec83f80,0x3f8e3f80,0x3ffb3f80,0x3ec83f44,0x3f8ebfed,0x3ffbbfed,0xbfd5bf44,0x3ffbbfb5,0xbfd53fb5,0x3ec8bfb5,0x3f8e3fb5,
0x3f8ebfed,0x3ffbbf44,0xbfd53f44,0xbec8bfed,0xbfc63f80,0xbe493f80,0x3fa2bf80,0x3fffbf80,0x3f713ec8,0x3f15bffb,0x3fe2bffb,0xbff5bec8,
0x3ff5bfed,0xbf713fed,0xbf15bf44,0x3fe23f44,0xbe49bf8e,0x3fa2bfd5,0xbfff3fd5,0xbfc6bf8e,0x3f80,0x3fb53f80,0x40003f80,0x3fb53f80,
0xc000,0xbfb50000,0xc0000000,0x3fb54000,0x4000,0xbfb5c000,0x40000000,0xbfb50000,0xc000,0x3fb50000,0xc0000000,0xbfb5c000,
0x3e493f80,0x3fc63f80,0x3fffbf80,0x3fa2bf80,0xbf15bffb,0xbf713ec8,0xbff53ec8,0x3fe23ffb,0x3f713fed,0xbff5bfed,0x3fe2bf44,0xbf153f44,
0xbfa2bfd5,0x3e49bf8e,0xbfc63f8e,0xbfffbfd5,0x3ec83f80,0x3fd53f80,0x3ffb3f80,0x3f8e3f80,0xbf8ebfed,0xbec83f44,0xbfd53f44,0x3ffb3fed,
0x3fd53fb5,0xbffbbfb5,0x3f8ebfb5,0x3ec83fb5,0xbffbbf44,0xbf8ebfed,0xbec83fed,0xbfd5bf44,0x3f153f80,0x3fe23f80,0x3ff5bf80,0x3f71bf80,
0xbfc6bfd5,0x3e493f8e,0xbfa23f8e,0x3fff3fd5,0x3fff3f44,0xbfc6bf44,0x3e49bfed,0x3fa23fed,0xbfe23ec8,0xbff5bffb,0x3f713ffb,0xbf153ec8,
0x3f443f80,0x3fed3f80,0x3fed3f80,0x3f443f80,0xbfedbfb5,0x3f443fb5,0xbf443fb5,0x3fed3fb5,0x3fed0000,0xbf440000,0xbf44c000,0x3fed4000,
0xbf443fb5,0xbfedbfb5,0x3fed3fb5,0x3f443fb5,0x3f713f80,0x3ff53f80,0x3fe2bf80,0x3f15bf80,0xbfffbf8e,0x3fa23fd5,0xbe493fd5,0x3fc63f8e,
0x3fa2bf44,0x3e493f44,0xbfc6bfed,0x3fff3fed,0x3f153ffb,0xbf71bec8,0x3ff53ec8,0x3fe23ffb,0x3f8e3f80,0x3ffb3f80,0x3fd53f80,0x3ec83f80,
0xbffbbf44,0x3fd53fed,0x3ec83fed,0x3f8e3f44,0x3ec8bfb5,0x3f8e3fb5,0xbffbbfb5,0x3fd53fb5,0x3fd53fed,0x3ec83f44,0x3f8ebf44,0x3ffb3fed,
0x3fa23f80,0x3fff3f80,0x3fc6bf80,0x3e49bf80,0xbfe2bec8,0x3ff53ffb,0x3f713ffb,0x3f153ec8,0xbf15bfed,0x3fe23fed,0xbff5bf44,0x3f713f44,
0x3fff3f8e,0x3fc63fd5,0xbe49bfd5,0x3fa23f8e,0x40004000,0x3fb54000,0x0,0xbfb50000,0x40004000,0xbfb50000,0x0,0xbfb5c000,
0x40004000,0xbfb5c000,0x0,0x3fb50000,0x40004000,0x3fb50000,0x0,0x3fb54000,0x3fa23fb5,0xbe493fb5,0xbfc6bfb5,0xbfffbfb5,
0x3f713f8e,0xbff5bfd5,0xbfe2bfd5,0x3f15bf8e,0x3f153f44,0x3f71bf44,0xbff5bfed,0x3fe23fed,0x3e493ec8,0x3fc63ffb,0xbfffbffb,0xbfa23ec8,
0xbec80000,0xbfd50000,0xbffbc000,0xbf8ec000,0xbf8ebf44,0xbec8bfed,0xbfd5bfed,0x3ffb3f44,0xbfd5bfb5,0x3ffb3fb5,0xbf8ebfb5,0xbec83fb5,
0xbffbbfed,0xbf8e3f44,0xbec8bf44,0xbfd5bfed,0xbfe2bfb5,0xbff5bfb5,0xbf71bfb5,0x3f15bfb5,0xbfffbffb,0x3fc6bec8,0x3e49bec8,0x3fa23ffb,
0xbfc6bfed,0x3e493fed,0x3fa23f44,0xbfffbf44,0xbf15bf8e,0xbfe2bfd5,0x3ff53fd5,0x3f71bf8e,0xbfedc000,0xbf44c000,0x3f440000,0x3fed0000,
0xbf44bfb5,0x3fed3fb5,0x3fed3fb5,0xbf443fb5,0x3f440000,0xbfed0000,0x3fed4000,0xbf44c000,0x3fed3fb5,0x3f44bfb5,0x3f443fb5,0x3fed3fb5,
0xbf15bfb5,0x3f71bfb5,0x3ff53fb5,0x3fe23fb5,0x3fa23ec8,0x3e493ffb,0x3fc63ffb,0xbfffbec8,0x3fff3fed,0xbfa2bfed,0xbe493f44,0x3fc6bf44,
0x3f713fd5,0x3ff53f8e,0xbfe2bf8e,0xbf153fd5,0x3f8e0000,0x3ffb0000,0x3fd54000,0x3ec84000,0x3ffb3fed,0xbfd53f44,0xbec83f44,0xbf8ebfed,
0x3ec83fb5,0x3f8ebfb5,0xbffbbfb5,0x3fd53fb5,0xbfd5bf44,0xbec83fed,0xbf8ebfed,0xbffbbf44,0x3fff3fb5,0x3fc63fb5,0x3e493fb5,0xbfa23fb5,
0x3f153fd5,0xbfe2bf8e,0xbff5bf8e,0x3f71bfd5,0xbfe2bf44,0x3ff53f44,0xbf71bfed,0xbf153fed,0xbfa2bffb,0xbfffbec8,0x3fc63ec8,0x3e49bffb,
0x4000,0xbfb54000,0xc0000000,0xbfb50000,0xc000,0x3fb50000,0x40000000,0xbfb54000,0x4000,0x3fb5c000,0xc0000000,0x3fb50000,
0xc000,0xbfb50000,0x40000000,0x3fb5c000,0xbfc63fb5,0xbfff3fb5,0xbfa2bfb5,0x3e49bfb5,0x3fe2bf8e,0xbf153fd5,0x3f713fd5,0xbff53f8e,
0xbff53f44,0x3fe2bf44,0xbf15bfed,0xbf713fed,0x3fffbec8,0x3fa2bffb,0x3e493ffb,0x3fc6bec8,0xbffb0000,0xbf8e0000,0x3ec8c000,0x3fd5c000,
0x3fd53f44,0xbffb3fed,0xbf8e3fed,0xbec8bf44,0xbf8ebfb5,0xbec83fb5,0x3fd5bfb5,0xbffb3fb5,0x3ec83fed,0x3fd5bf44,0xbffb3f44,0xbf8e3fed,
0xbf71bfb5,0x3f15bfb5,0x3fe2bfb5,0x3ff5bfb5,0xbe493ffb,0xbfa23ec8,0xbfff3ec8,0x3fc6bffb,0x3fa2bfed,0xbfff3fed,0x3fc63f44,0xbe49bf44,
0xbff53f8e,0xbf713fd5,0xbf15bfd5,0xbfe23f8e,0x3f44c000,0x3fedc000,0x3fed0000,0x3f440000,0xbfed3fb5,0x3f44bfb5,0xbf44bfb5,0x3fedbfb5,
0x3fed0000,0xbf440000,0xbf444000,0x3fedc000,0xbf44bfb5,0xbfed3fb5,0x3fedbfb5,0x3f44bfb5,0x3ff5bfb5,0x3fe2bfb5,0x3f153fb5,0xbf713fb5,
0xbfc6bec8,0x3fffbffb,0x3fa2bffb,0x3e493ec8,0xbe493fed,0x3fc6bfed,0xbfff3f44,0x3fa2bf44,0x3fe2bfd5,0x3f15bf8e,0x3f713f8e,0x3ff5bfd5,
0x3fd50000,0x3ec80000,0xbf8e4000,0xbffb4000,0x3ec8bfed,0x3f8ebf44,0x3ffbbf44,0xbfd53fed,0xbffb3fb5,0x3fd5bfb5,0xbec8bfb5,0xbf8e3fb5,
0x3f8e3f44,0x3ffbbfed,0xbfd53fed,0xbec83f44,0x3e493fb5,0xbfa23fb5,0xbfff3fb5,0xbfc63fb5,0x3ff5bfd5,0xbf713f8e,0x3f153f8e,0xbfe23fd5,
0xbf71bf44,0xbf153f44,0x3fe2bfed,0xbff53fed,0xbfc63ffb,0xbe493ec8,0xbfa2bec8,0xbfff3ffb,0xc0004000,0xbfb54000,0x0,0x3fb50000,
0xc0004000,0x3fb50000,0x0,0x3fb5c000,0xc0004000,0x3fb5c000,0x0,0xbfb50000,0xc0004000,0xbfb50000,0x0,0xbfb54000,
0xbfa23fb5,0x3e493fb5,0x3fc6bfb5,0x3fffbfb5,0xbf713f8e,0x3ff5bfd5,0x3fe2bfd5,0xbf15bf8e,0xbf153f44,0xbf71bf44,0x3ff5bfed,0xbfe23fed,
0xbe493ec8,0xbfc63ffb,0x3fffbffb,0x3fa23ec8,0x3ec80000,0x3fd50000,0x3ffbc000,0x3f8ec000,0x3f8ebf44,0x3ec8bfed,0x3fd5bfed,0xbffb3f44,
0x3fd5bfb5,0xbffb3fb5,0x3f8ebfb5,0x3ec83fb5,0x3ffbbfed,0x3f8e3f44,0x3ec8bf44,0x3fd5bfed,0x3fe2bfb5,0x3ff5bfb5,0x3f71bfb5,0xbf15bfb5,
0x3fffbffb,0xbfc6bec8,0xbe49bec8,0xbfa23ffb,0x3fc6bfed,0xbe493fed,0xbfa23f44,0x3fffbf44,0x3f15bf8e,0x3fe2bfd5,0xbff53fd5,0xbf71bf8e,
0x3fedc000,0x3f44c000,0xbf440000,0xbfed0000,0x3f44bfb5,0xbfed3fb5,0xbfed3fb5,0x3f443fb5,0xbf440000,0x3fed0000,0xbfed4000,0x3f44c000,
0xbfed3fb5,0xbf44bfb5,0xbf443fb5,0xbfed3fb5,0x3f15bfb5,0xbf71bfb5,0xbff53fb5,0xbfe23fb5,0xbfa23ec8,0xbe493ffb,0xbfc63ffb,0x3fffbec8,
0xbfff3fed,0x3fa2bfed,0x3e493f44,0xbfc6bf44,0xbf713fd5,0xbff53f8e,0x3fe2bf8e,0x3f153fd5,0xbf8e0000,0xbffb0000,0xbfd54000,0xbec84000,
0xbffb3fed,0x3fd53f44,0x3ec83f44,0x3f8ebfed,0xbec83fb5,0xbf8ebfb5,0x3ffbbfb5,0xbfd53fb5,0x3fd5bf44,0x3ec83fed,0x3f8ebfed,0x3ffbbf44,
0xbfff3fb5,0xbfc63fb5,0xbe493fb5,0x3fa23fb5,0xbf153fd5,0x3fe2bf8e,0x3ff5bf8e,0xbf71bfd5,0x3fe2bf44,0xbff53f44,0x3f71bfed,0x3f153fed,
0x3fa2bffb,0x3fffbec8,0xbfc63ec8,0xbe49bffb,0x4000,0x3fb54000,0x40000000,0x3fb50000,0xc000,0xbfb50000,0xc0000000,0x3fb54000,
0x4000,0xbfb5c000,0x40000000,0xbfb50000,0xc000,0x3fb50000,0xc0000000,0xbfb5c000,0x3fc63fb5,0x3fff3fb5,0x3fa2bfb5,0xbe49bfb5,
0xbfe2bf8e,0x3f153fd5,0xbf713fd5,0x3ff53f8e,0x3ff53f44,0xbfe2bf44,0x3f15bfed,0x3f713fed,0xbfffbec8,0xbfa2bffb,0xbe493ffb,0xbfc6bec8,
0x3ffb0000,0x3f8e0000,0xbec8c000,0xbfd5c000,0xbfd53f44,0x3ffb3fed,0x3f8e3fed,0x3ec8bf44,0x3f8ebfb5,0x3ec83fb5,0xbfd5bfb5,0x3ffb3fb5,
0xbec83fed,0xbfd5bf44,0x3ffb3f44,0x3f8e3fed,0x3f71bfb5,0xbf15bfb5,0xbfe2bfb5,0xbff5bfb5,0x3e493ffb,0x3fa23ec8,0x3fff3ec8,0xbfc6bffb,
0xbfa2bfed,0x3fff3fed,0xbfc63f44,0x3e49bf44,0x3ff53f8e,0x3f713fd5,0x3f15bfd5,0x3fe23f8e,0xbf44c000,0xbfedc000,0xbfed0000,0xbf440000,
0x3fed3fb5,0xbf44bfb5,0x3f44bfb5,0xbfedbfb5,0xbfed0000,0x3f440000,0x3f444000,0xbfedc000,0x3f44bfb5,0x3fed3fb5,0xbfedbfb5,0xbf44bfb5,
0xbff5bfb5,0xbfe2bfb5,0xbf153fb5,0x3f713fb5,0x3fc6bec8,0xbfffbffb,0xbfa2bffb,0xbe493ec8,0x3e493fed,0xbfc6bfed,0x3fff3f44,0xbfa2bf44,
0xbfe2bfd5,0xbf15bf8e,0xbf713f8e,0xbff5bfd5,0xbfd50000,0xbec80000,0x3f8e4000,0x3ffb4000,0xbec8bfed,0xbf8ebf44,0xbffbbf44,0x3fd53fed,
0x3ffb3fb5,0xbfd5bfb5,0x3ec8bfb5,0x3f8e3fb5,0xbf8e3f44,0xbffbbfed,0x3fd53fed,0x3ec83f44,0xbe493fb5,0x3fa23fb5,0x3fff3fb5,0x3fc63fb5,
0xbff5bfd5,0x3f713f8e,0xbf153f8e,0x3fe23fd5,0x3f71bf44,0x3f153f44,0xbfe2bfed,0x3ff53fed,0x3fc63ffb,0x3e493ec8,0x3fa2bec8,0x3fff3ffb,
0x40004000,0x3fb54000,0x0,0xbfb50000,0x40004000,0xbfb50000,0x0,0xbfb5c000,0x40004000,0xbfb5c000,0x0,0x3fb50000,
0x40004000,0x3fb50000,0x0,0x3fb54000,0xbe490000,0xbfc60000,0xbfffc000,0xbfa2c000,0xbf15bec8,0xbf71bffb,0xbff5bffb,0x3fe23ec8,
0xbf71bf44,0x3ff53f44,0xbfe2bfed,0x3f153fed,0xbfa2bf8e,0x3e493fd5,0xbfc6bfd5,0xbfffbf8e,0xbffbc000,0xbf8ec000,0x3ec80000,0x3fd50000,
0xbfd5bfed,0x3ffb3f44,0x3f8e3f44,0x3ec83fed,0xbf8ebfb5,0xbec83fb5,0x3fd53fb5,0xbffbbfb5,0xbec8bf44,0xbfd5bfed,0x3ffb3fed,0x3f8ebf44,
0x3f150000,0x3fe20000,0x3ff54000,0x3f714000,0x3fc63f8e,0xbe493fd5,0x3fa23fd5,0xbfffbf8e,0x3fff3fed,0xbfc6bfed,0x3e493f44,0x3fa2bf44,
0x3fe23ffb,0x3ff53ec8,0xbf71bec8,0x3f153ffb,0x3fed4000,0x3f444000,0xbf440000,0xbfed0000,0x3f443fb5,0xbfedbfb5,0xbfedbfb5,0x3f44bfb5,
0xbf440000,0x3fed0000,0xbfedc000,0x3f444000,0xbfedbfb5,0xbf443fb5,0xbf44bfb5,0xbfedbfb5,0xbf710000,0xbff50000,0xbfe2c000,0xbf15c000,
0xbfffbfd5,0x3fa2bf8e,0xbe49bf8e,0x3fc63fd5,0xbfa2bfed,0xbe493fed,0x3fc63f44,0xbfffbf44,0x3f15bec8,0xbf71bffb,0x3ff53ffb,0x3fe2bec8,
0xbfd5c000,0xbec8c000,0x3f8e0000,0x3ffb0000,0x3ec8bf44,0x3f8e3fed,0x3ffb3fed,0xbfd53f44,0x3ffb3fb5,0xbfd5bfb5,0x3ec83fb5,0x3f8ebfb5,
0x3f8e3fed,0x3ffb3f44,0xbfd5bf44,0xbec83fed,0x3fa20000,0x3fff0000,0x3fc64000,0x3e494000,0x3fe23ffb,0xbff53ec8,0xbf713ec8,0xbf15bffb,
0xbf153f44,0x3fe2bf44,0xbff5bfed,0x3f713fed,0xbfffbfd5,0xbfc63f8e,0x3e49bf8e,0xbfa2bfd5,0x4000,0xbfb54000,0xc0000000,0xbfb50000,
0xc000,0x3fb50000,0x40000000,0xbfb54000,0x4000,0x3fb5c000,0xc0000000,0x3fb50000,0xc000,0xbfb50000,0x40000000,0x3fb5c000,
0xbfff0000,0xbfa20000,0x3e49c000,0x3fc6c000,0x3ff53ec8,0xbfe23ffb,0xbf153ffb,0xbf71bec8,0xbfe2bf44,0x3f153f44,0x3f71bfed,0xbff53fed,
0x3fc63f8e,0x3fffbfd5,0xbfa23fd5,0x3e493f8e,0x3ec8c000,0x3fd5c000,0x3ffb0000,0x3f8e0000,0xbf8e3fed,0xbec8bf44,0xbfd5bf44,0x3ffbbfed,
0x3fd5bfb5,0xbffb3fb5,0x3f8e3fb5,0x3ec8bfb5,0xbffb3f44,0xbf8e3fed,0xbec8bfed,0xbfd53f44,0x3ff50000,0x3f710000,0xbf154000,0xbfe24000,
0xbfa2bf8e,0x3fffbfd5,0x3fc6bfd5,0xbe493f8e,0x3e493fed,0x3fa2bfed,0xbfff3f44,0x3fc6bf44,0x3f71bffb,0xbf15bec8,0x3fe23ec8,0x3ff5bffb,
0xbf444000,0xbfed4000,0xbfed0000,0xbf440000,0x3fedbfb5,0xbf443fb5,0x3f443fb5,0xbfed3fb5,0xbfed0000,0x3f440000,0x3f44c000,0xbfed4000,
0x3f443fb5,0x3fedbfb5,0xbfed3fb5,0xbf443fb5,0xbfe20000,0xbf150000,0x3f71c000,0x3ff5c000,0x3e493fd5,0xbfc63f8e,0xbfff3f8e,0x3fa2bfd5,
0x3fc6bfed,0xbfff3fed,0x3fa23f44,0x3e49bf44,0xbff53ec8,0xbfe23ffb,0x3f15bffb,0xbf713ec8,0x3f8ec000,0x3ffbc000,0x3fd50000,0x3ec80000,
0xbffb3f44,0x3fd5bfed,0x3ec8bfed,0x3f8ebf44,0x3ec83fb5,0x3f8ebfb5,0xbffb3fb5,0x3fd5bfb5,0x3fd5bfed,0x3ec8bf44,0x3f8e3f44,0x3ffbbfed,
0x3fc60000,0x3e490000,0xbfa24000,0xbfff4000,0x3f71bffb,0x3f15bec8,0x3fe2bec8,0xbff53ffb,0xbff53f44,0x3f71bf44,0x3f15bfed,0xbfe23fed,
0xbe493fd5,0x3fa2bf8e,0xbfff3f8e,0xbfc63fd5,0xc0004000,0xbfb54000,0x0,0x3fb50000,0xc0004000,0x3fb50000,0x0,0x3fb5c000,
0xc0004000,0x3fb5c000,0x0,0xbfb50000,0xc0004000,0xbfb50000,0x0,0xbfb54000,0x3e490000,0x3fc60000,0x3fffc000,0x3fa2c000,
0x3f15bec8,0x3f71bffb,0x3ff5bffb,0xbfe23ec8,0x3f71bf44,0xbff53f44,0x3fe2bfed,0xbf153fed,0x3fa2bf8e,0xbe493fd5,0x3fc6bfd5,0x3fffbf8e,
0x3ffbc000,0x3f8ec000,0xbec80000,0xbfd50000,0x3fd5bfed,0xbffb3f44,0xbf8e3f44,0xbec83fed,0x3f8ebfb5,0x3ec83fb5,0xbfd53fb5,0x3ffbbfb5,
0x3ec8bf44,0x3fd5bfed,0xbffb3fed,0xbf8ebf44,0xbf150000,0xbfe20000,0xbff54000,0xbf714000,0xbfc63f8e,0x3e493fd5,0xbfa23fd5,0x3fffbf8e,
0xbfff3fed,0x3fc6bfed,0xbe493f44,0xbfa2bf44,0xbfe23ffb,0xbff53ec8,0x3f71bec8,0xbf153ffb,0xbfed4000,0xbf444000,0x3f440000,0x3fed0000,
0xbf443fb5,0x3fedbfb5,0x3fedbfb5,0xbf44bfb5,0x3f440000,0xbfed0000,0x3fedc000,0xbf444000,0x3fedbfb5,0x3f443fb5,0x3f44bfb5,0x3fedbfb5,
0x3f710000,0x3ff50000,0x3fe2c000,0x3f15c000,0x3fffbfd5,0xbfa2bf8e,0x3e49bf8e,0xbfc63fd5,0x3fa2bfed,0x3e493fed,0xbfc63f44,0x3fffbf44,
0xbf15bec8,0x3f71bffb,0xbff53ffb,0xbfe2bec8,0x3fd5c000,0x3ec8c000,0xbf8e0000,0xbffb0000,0xbec8bf44,0xbf8e3fed,0xbffb3fed,0x3fd53f44,
0xbffb3fb5,0x3fd5bfb5,0xbec83fb5,0xbf8ebfb5,0xbf8e3fed,0xbffb3f44,0x3fd5bf44,0x3ec83fed,0xbfa20000,0xbfff0000,0xbfc64000,0xbe494000,
0xbfe23ffb,0x3ff53ec8,0x3f713ec8,0x3f15bffb,0x3f153f44,0xbfe2bf44,0x3ff5bfed,0xbf713fed,0x3fffbfd5,0x3fc63f8e,0xbe49bf8e,0x3fa2bfd5,
0x4000,0x3fb54000,0x40000000,0x3fb50000,0xc000,0xbfb50000,0xc0000000,0x3fb54000,0x4000,0xbfb5c000,0x40000000,0xbfb50000,
0xc000,0x3fb50000,0xc0000000,0xbfb5c000,0x3fff0000,0x3fa20000,0xbe49c000,0xbfc6c000,0xbff53ec8,0x3fe23ffb,0x3f153ffb,0x3f71bec8,
0x3fe2bf44,0xbf153f44,0xbf71bfed,0x3ff53fed,0xbfc63f8e,0xbfffbfd5,0x3fa23fd5,0xbe493f8e,0xbec8c000,0xbfd5c000,0xbffb0000,0xbf8e0000,
0x3f8e3fed,0x3ec8bf44,0x3fd5bf44,0xbffbbfed,0xbfd5bfb5,0x3ffb3fb5,0xbf8e3fb5,0xbec8bfb5,0x3ffb3f44,0x3f8e3fed,0x3ec8bfed,0x3fd53f44,
0xbff50000,0xbf710000,0x3f154000,0x3fe24000,0x3fa2bf8e,0xbfffbfd5,0xbfc6bfd5,0x3e493f8e,0xbe493fed,0xbfa2bfed,0x3fff3f44,0xbfc6bf44,
0xbf71bffb,0x3f15bec8,0xbfe23ec8,0xbff5bffb,0x3f444000,0x3fed4000,0x3fed0000,0x3f440000,0xbfedbfb5,0x3f443fb5,0xbf443fb5,0x3fed3fb5,
0x3fed0000,0xbf440000,0xbf44c000,0x3fed4000,0xbf443fb5,0xbfedbfb5,0x3fed3fb5,0x3f443fb5,0x3fe20000,0x3f150000,0xbf71c000,0xbff5c000,
0xbe493fd5,0x3fc63f8e,0x3fff3f8e,0xbfa2bfd5,0xbfc6bfed,0x3fff3fed,0xbfa23f44,0xbe49bf44,0x3ff53ec8,0x3fe23ffb,0xbf15bffb,0x3f713ec8,
0xbf8ec000,0xbffbc000,0xbfd50000,0xbec80000,0x3ffb3f44,0xbfd5bfed,0xbec8bfed,0xbf8ebf44,0xbec83fb5,0xbf8ebfb5,0x3ffb3fb5,0xbfd5bfb5,
0xbfd5bfed,0xbec8bf44,0xbf8e3f44,0xbffbbfed,0xbfc60000,0xbe490000,0x3fa24000,0x3fff4000,0xbf71bffb,0xbf15bec8,0xbfe2bec8,0x3ff53ffb,
0x3ff53f44,0xbf71bf44,0xbf15bfed,0x3fe23fed,0x3e493fd5,0xbfa2bf8e,0x3fff3f8e,0x3fc63fd5,0x40004000,0x3fb54000,0x0,0xbfb50000,
0x40004000,0xbfb50000,0x0,0xbfb5c000,0x40004000,0xbfb5c000,0x0,0x3fb50000,0x40004000,0x3fb50000,0x0,0x3fb54000,
0xbfc6bfb5,0xbfffbfb5,0xbfa2bfb5,0x3e49bfb5,0xbfe2bfd5,0x3f15bf8e,0xbf71bf8e,0x3ff53fd5,0xbff5bfed,0x3fe23fed,0xbf15bf44,0xbf713f44,
0xbfffbffb,0xbfa23ec8,0xbe49bec8,0xbfc6bffb,0x3ec80000,0x3fd50000,0x3ffb4000,0x3f8e4000,0x3f8e3f44,0x3ec83fed,0x3fd53fed,0xbffbbf44,
0x3fd53fb5,0xbffbbfb5,0x3f8e3fb5,0x3ec8bfb5,0x3ffb3fed,0x3f8ebf44,0x3ec83f44,0x3fd53fed,0x3f713fb5,0xbf153fb5,0xbfe2bfb5,0xbff5bfb5,
0xbe493ec8,0xbfa2bffb,0xbfffbffb,0x3fc6bec8,0xbfa2bf44,0x3fff3f44,0xbfc6bfed,0x3e493fed,0xbff5bfd5,0xbf713f8e,0xbf15bf8e,0xbfe2bfd5,
0xbfedc000,0xbf44c000,0x3f440000,0x3fed0000,0xbf44bfb5,0x3fed3fb5,0x3fed3fb5,0xbf443fb5,0x3f440000,0xbfed0000,0x3fed4000,0xbf44c000,
0x3fed3fb5,0x3f44bfb5,0x3f443fb5,0x3fed3fb5,0x3ff53fb5,0x3fe23fb5,0x3f153fb5,0xbf713fb5,0x3fc63ffb,0xbfffbec8,0xbfa2bec8,0xbe49bffb,
0xbe493f44,0x3fc6bf44,0xbfffbfed,0x3fa23fed,0xbfe2bf8e,0xbf153fd5,0xbf71bfd5,0xbff5bf8e,0xbf8e0000,0xbffb0000,0xbfd5c000,0xbec8c000,
0xbffbbfed,0x3fd5bf44,0x3ec8bf44,0x3f8e3fed,0xbec8bfb5,0xbf8e3fb5,0x3ffb3fb5,0xbfd5bfb5,0x3fd53f44,0x3ec8bfed,0x3f8e3fed,0x3ffb3f44,
0xbe49bfb5,0x3fa2bfb5,0x3fff3fb5,0x3fc63fb5,0x3ff53f8e,0xbf713fd5,0x3f153fd5,0xbfe2bf8e,0x3f713fed,0x3f15bfed,0xbfe2bf44,0x3ff53f44,
0xbfc6bec8,0xbe493ffb,0xbfa2bffb,0xbfffbec8,0x4000,0xbfb54000,0xc0000000,0xbfb50000,0xc000,0x3fb50000,0x40000000,0xbfb54000,
0x4000,0x3fb5c000,0xc0000000,0x3fb50000,0xc000,0xbfb50000,0x40000000,0x3fb5c000,0xbfa2bfb5,0x3e49bfb5,0x3fc6bfb5,0x3fffbfb5,
0x3f713fd5,0xbff53f8e,0xbfe23f8e,0x3f15bfd5,0xbf15bfed,0xbf713fed,0x3ff5bf44,0xbfe23f44,0x3e493ffb,0x3fc6bec8,0xbfff3ec8,0xbfa23ffb,
0x3ffb0000,0x3f8e0000,0xbec84000,0xbfd54000,0xbfd5bf44,0x3ffbbfed,0x3f8ebfed,0x3ec83f44,0x3f8e3fb5,0x3ec8bfb5,0xbfd53fb5,0x3ffbbfb5,
0xbec8bfed,0xbfd53f44,0x3ffbbf44,0x3f8ebfed,0xbfe23fb5,0xbff53fb5,0xbf71bfb5,0x3f15bfb5,0x3fffbec8,0xbfc63ffb,0xbe493ffb,0xbfa23ec8,
0xbfc6bf44,0x3e493f44,0x3fa2bfed,0xbfff3fed,0x3f153fd5,0x3fe2bf8e,0xbff53f8e,0xbf713fd5,0x3f44c000,0x3fedc000,0x3fed0000,0x3f440000,
0xbfed3fb5,0x3f44bfb5,0xbf44bfb5,0x3fedbfb5,0x3fed0000,0xbf440000,0xbf444000,0x3fedc000,0xbf44bfb5,0xbfed3fb5,0x3fedbfb5,0x3f44bfb5,
0x3f153fb5,0xbf713fb5,0xbff53fb5,0xbfe23fb5,0x3fa2bffb,0x3e493ec8,0x3fc63ec8,0xbfff3ffb,0xbfff3f44,0x3fa2bf44,0x3e49bfed,0xbfc63fed,
0x3f713f8e,0x3ff5bfd5,0xbfe23fd5,0xbf153f8e,0xbfd50000,0xbec80000,0x3f8ec000,0x3ffbc000,0xbec83fed,0xbf8e3f44,0xbffb3f44,0x3fd5bfed,
0x3ffbbfb5,0xbfd53fb5,0x3ec83fb5,0x3f8ebfb5,0xbf8ebf44,0xbffb3fed,0x3fd5bfed,0x3ec8bf44,0x3fffbfb5,0x3fc6bfb5,0x3e493fb5,0xbfa23fb5,
0xbf15bf8e,0x3fe2bfd5,0x3ff5bfd5,0xbf713f8e,0xbfe23fed,0x3ff5bfed,0xbf71bf44,0xbf153f44,0x3fa23ec8,0x3fffbffb,0xbfc63ffb,0xbe493ec8,
0xc0004000,0xbfb54000,0x0,0x3fb50000,0xc0004000,0x3fb50000,0x0,0x3fb5c000,0xc0004000,0x3fb5c000,0x0,0xbfb50000,
0xc0004000,0xbfb50000,0x0,0xbfb54000,0x3fc6bfb5,0x3fffbfb5,0x3fa2bfb5,0xbe49bfb5,0x3fe2bfd5,0xbf15bf8e,0x3f71bf8e,0xbff53fd5,
0x3ff5bfed,0xbfe23fed,0x3f15bf44,0x3f713f44,0x3fffbffb,0x3fa23ec8,0x3e49bec8,0x3fc6bffb,0xbec80000,0xbfd50000,0xbffb4000,0xbf8e4000,
0xbf8e3f44,0xbec83fed,0xbfd53fed,0x3ffbbf44,0xbfd53fb5,0x3ffbbfb5,0xbf8e3fb5,0xbec8bfb5,0xbffb3fed,0xbf8ebf44,0xbec83f44,0xbfd53fed,
0xbf713fb5,0x3f153fb5,0x3fe2bfb5,0x3ff5bfb5,0x3e493ec8,0x3fa2bffb,0x3fffbffb,0xbfc6bec8,0x3fa2bf44,0xbfff3f44,0x3fc6bfed,0xbe493fed,
0x3ff5bfd5,0x3f713f8e,0x3f15bf8e,0x3fe2bfd5,0x3fedc000,0x3f44c000,0xbf440000,0xbfed0000,0x3f44bfb5,0xbfed3fb5,0xbfed3fb5,0x3f443fb5,
0xbf440000,0x3fed0000,0xbfed4000,0x3f44c000,0xbfed3fb5,0xbf44bfb5,0xbf443fb5,0xbfed3fb5,0xbff53fb5,0xbfe23fb5,0xbf153fb5,0x3f713fb5,
0xbfc63ffb,0x3fffbec8,0x3fa2bec8,0x3e49bffb,0x3e493f44,0xbfc6bf44,0x3fffbfed,0xbfa23fed,0x3fe2bf8e,0x3f153fd5,0x3f71bfd5,0x3ff5bf8e,
0x3f8e0000,0x3ffb0000,0x3fd5c000,0x3ec8c000,0x3ffbbfed,0xbfd5bf44,0xbec8bf44,0xbf8e3fed,0x3ec8bfb5,0x3f8e3fb5,0xbffb3fb5,0x3fd5bfb5,
0xbfd53f44,0xbec8bfed,0xbf8e3fed,0xbffb3f44,0x3e49bfb5,0xbfa2bfb5,0xbfff3fb5,0xbfc63fb5,0xbff53f8e,0x3f713fd5,0xbf153fd5,0x3fe2bf8e,
0xbf713fed,0xbf15bfed,0x3fe2bf44,0xbff53f44,0x3fc6bec8,0x3e493ffb,0x3fa2bffb,0x3fffbec8,0x4000,0x3fb54000,0x40000000,0x3fb50000,
0xc000,0xbfb50000,0xc0000000,0x3fb54000,0x4000,0xbfb5c000,0x40000000,0xbfb50000,0xc000,0x3fb50000,0xc0000000,0xbfb5c000,
0x3fa2bfb5,0xbe49bfb5,0xbfc6bfb5,0xbfffbfb5,0xbf713fd5,0x3ff53f8e,0x3fe23f8e,0xbf15bfd5,0x3f15bfed,0x3f713fed,0xbff5bf44,0x3fe23f44,
0xbe493ffb,0xbfc6bec8,0x3fff3ec8,0x3fa23ffb,0xbffb0000,0xbf8e0000,0x3ec84000,0x3fd54000,0x3fd5bf44,0xbffbbfed,0xbf8ebfed,0xbec83f44,
0xbf8e3fb5,0xbec8bfb5,0x3fd53fb5,0xbffbbfb5,0x3ec8bfed,0x3fd53f44,0xbffbbf44,0xbf8ebfed,0x3fe23fb5,0x3ff53fb5,0x3f71bfb5,0xbf15bfb5,
0xbfffbec8,0x3fc63ffb,0x3e493ffb,0x3fa23ec8,0x3fc6bf44,0xbe493f44,0xbfa2bfed,0x3fff3fed,0xbf153fd5,0xbfe2bf8e,0x3ff53f8e,0x3f713fd5,
0xbf44c000,0xbfedc000,0xbfed0000,0xbf440000,0x3fed3fb5,0xbf44bfb5,0x3f44bfb5,0xbfedbfb5,0xbfed0000,0x3f440000,0x3f444000,0xbfedc000,
0x3f44bfb5,0x3fed3fb5,0xbfedbfb5,0xbf44bfb5,0xbf153fb5,0x3f713fb5,0x3ff53fb5,0x3fe23fb5,0xbfa2bffb,0xbe493ec8,0xbfc63ec8,0x3fff3ffb,
0x3fff3f44,0xbfa2bf44,0xbe49bfed,0x3fc63fed,0xbf713f8e,0xbff5bfd5,0x3fe23fd5,0x3f153f8e,0x3fd50000,0x3ec80000,0xbf8ec000,0xbffbc000,
0x3ec83fed,0x3f8e3f44,0x3ffb3f44,0xbfd5bfed,0xbffbbfb5,0x3fd53fb5,0xbec83fb5,0xbf8ebfb5,0x3f8ebf44,0x3ffb3fed,0xbfd5bfed,0xbec8bf44,
0xbfffbfb5,0xbfc6bfb5,0xbe493fb5,0x3fa23fb5,0x3f15bf8e,0xbfe2bfd5,0xbff5bfd5,0x3f713f8e,0x3fe23fed,0xbff5bfed,0x3f71bf44,0x3f153f44,
0xbfa23ec8,0xbfffbffb,0x3fc63ffb,0x3e493ec8,0x80003f80,0x3f800000,0x80003f80,0x3f800000,0x80003f80,0x3f800000,0x80003f80,0x3f800000,
0x80003f80,0x3f800000,0x80003f80,0x3f800000,0x80003f80,0x3f800000,0x80003f80,0x3f800000,0x80003f80,0x3f800000,0x8000bf80,0xbf800000,
0x3f353f35,0x3f35bf35,0xbf35bf35,0xbf353f35,0x3f800000,0xbf80,0xbf800000,0x3f80,0x3f35bf35,0xbf35bf35,0xbf353f35,0x3f353f35,
0x80003f80,0x3f800000,0x80003f80,0x3f800000,0x3f800000,0xbf80,0x3f800000,0xbf80,0x8000bf80,0xbf800000,0x8000bf80,0xbf800000,
0xbf800000,0x3f80,0xbf800000,0x3f80,0x80003f80,0x3f800000,0x8000bf80,0xbf800000,0x3f35bf35,0xbf35bf35,0xbf353f35,0x3f353f35,
0xbf800000,0x3f80,0x3f800000,0xbf80,0x3f353f35,0x3f35bf35,0xbf35bf35,0xbf353f35,0x80003f80,0x3f800000,0x80003f80,0x3f800000,
0x8000bf80,0xbf800000,0x8000bf80,0xbf800000,0x80003f80,0x3f800000,0x80003f80,0x3f800000,0x8000bf80,0xbf800000,0x8000bf80,0xbf800000,
0x80003f80,0x3f800000,0x8000bf80,0xbf800000,0xbf35bf35,0xbf353f35,0x3f353f35,0x3f35bf35,0x3f800000,0xbf80,0xbf800000,0x3f80,
0xbf353f35,0x3f353f35,0x3f35bf35,0xbf35bf35,0x80003f80,0x3f800000,0x80003f80,0x3f800000,0xbf800000,0x3f80,0xbf800000,0x3f80,
0x8000bf80,0xbf800000,0x8000bf80,0xbf800000,0x3f800000,0xbf80,0x3f800000,0xbf80,0x80003f80,0x3f800000,0x8000bf80,0xbf800000,
0xbf353f35,0x3f353f35,0x3f35bf35,0xbf35bf35,0xbf800000,0x3f80,0x3f800000,0xbf80,0xbf35bf35,0xbf353f35,0x3f353f35,0x3f35bf35,
0x3f803f80,0x80008000,0x80008000,0xbf80bf80,0x3f803f80,0x80008000,0x80008000,0xbf80bf80,0x3f803f80,0x80008000,0x80008000,0xbf80bf80,
0x3f803f80,0x80008000,0x80008000,0xbf80bf80,0x3f353f80,0x3f358000,0x3f358000,0xbf35bf80,0xbf350000,0x3f353f80,0x3f353f80,0x3f358000,
0xbf35bf80,0xbf358000,0xbf358000,0x3f353f80,0x3f350000,0xbf35bf80,0xbf35bf80,0xbf358000,0x3f80,0x3f808000,0x3f808000,0x8000bf80,
0xbf80,0xbf808000,0xbf808000,0x80003f80,0x3f80,0x3f808000,0x3f808000,0x8000bf80,0xbf80,0xbf808000,0xbf808000,0x80003f80,
0xbf353f80,0x3f358000,0x3f358000,0x3f35bf80,0x3f350000,0x3f35bf80,0x3f35bf80,0xbf358000,0x3f35bf80,0xbf358000,0xbf358000,0xbf353f80,
0xbf350000,0xbf353f80,0xbf353f80,0x3f358000,0xbf803f80,0x80008000,0x80008000,0x3f80bf80,0xbf803f80,0x80008000,0x80008000,0x3f80bf80,
0xbf803f80,0x80008000,0x80008000,0x3f80bf80,0xbf803f80,0x80008000,0x80008000,0x3f80bf80,0xbf353f80,0xbf358000,0xbf358000,0x3f35bf80,
0x3f350000,0xbf353f80,0xbf353f80,0xbf358000,0x3f35bf80,0x3f358000,0x3f358000,0xbf353f80,0xbf350000,0x3f35bf80,0x3f35bf80,0x3f358000,
0x3f80,0xbf808000,0xbf808000,0x8000bf80,0xbf80,0x3f808000,0x3f808000,0x80003f80,0x3f80,0xbf808000,0xbf808000,0x8000bf80,
0xbf80,0x3f808000,0x3f808000,0x80003f80,0x3f353f80,0xbf358000,0xbf358000,0xbf35bf80,0xbf350000,0xbf35bf80,0xbf35bf80,0x3f358000,
0xbf35bf80,0x3f358000,0x3f358000,0x3f353f80,0x3f350000,0x3f353f80,0x3f353f80,0xbf358000,0x3f800000,0x0,0x3f800000,0x0,
0x3f800000,0x0,0x3f800000,0x0,0x3f800000,0x0,0x3f800000,0x0,0x3f800000,0x0,0x3f800000,0x0,
0x3f800000,0x0,0x3f7fb10f,0xbd48fb30,0x3f7ec46d,0xbdc8bd36,0x3f7d3aac,0xbe164083,0x3f7b14be,0xbe47c5c2,0x3f7853f8,0xbe78cfcc,
0x3f74fa0b,0xbe94a031,0x3f710908,0xbeac7cd4,0x3f800000,0x0,0x3f7ec46d,0xbdc8bd36,0x3f7b14be,0xbe47c5c2,0x3f74fa0b,0xbe94a031,
0x3f6c835e,0xbec3ef15,0x3f61c598,0xbef15aea,0x3f54db31,0xbf0e39da,0x3f45e403,0xbf226799,0x3f800000,0x0,0x3f7d3aac,0xbe164083,
0x3f74fa0b,0xbe94a031,0x3f676bd8,0xbedae880,0x3f54db31,0xbf0e39da,0x3f3daef9,0xbf2beb4a,0x3f226799,0xbf45e403,0x3f039c3d,0xbf5b941a,
0x3f800000,0x0,0x3f7b14be,0xbe47c5c2,0x3f6c835e,0xbec3ef15,0x3f54db31,0xbf0e39da,0x3f3504f3,0xbf3504f3,0x3f0e39da,0xbf54db31,
0x3ec3ef15,0xbf6c835e,0x3e47c5c2,0xbf7b14be,0x3f800000,0x0,0x3f7853f8,0xbe78cfcc,0x3f61c598,0xbef15aea,0x3f3daef9,0xbf2beb4a,
0x3f0e39da,0xbf54db31,0x3eac7cd4,0xbf710908,0x3dc8bd36,0xbf7ec46d,0xbe164083,0xbf7d3aac,0x3f800000,0x0,0x3f74fa0b,0xbe94a031,
0x3f54db31,0xbf0e39da,0x3f226799,0xbf45e403,0x3ec3ef15,0xbf6c835e,0x3dc8bd36,0xbf7ec46d,0xbe47c5c2,0xbf7b14be,0xbef15aea,0xbf61c598,
0x3f800000,0x0,0x3f710908,0xbeac7cd4,0x3f45e403,0xbf226799,0x3f039c3d,0xbf5b941a,0x3e47c5c2,0xbf7b14be,0xbe164083,0xbf7d3aac,
0xbef15aea,0xbf61c598,0xbf3daef9,0xbf2beb4a,0x3f800000,0x0,0x3f800000,0x0,0x3f800000,0x0,0x3f800000,0x0,
0x3f800000,0x0,0x3f800000,0x0,0x3f800000,0x0,0x3f800000,0x0,0x3f6c835e,0xbec3ef15,0x3f676bd8,0xbedae880,
0x3f61c598,0xbef15aea,0x3f5b941a,0xbf039c3d,0x3f54db31,0xbf0e39da,0x3f4d9f02,0xbf187fc0,0x3f45e403,0xbf226799,0x3f3daef9,0xbf2beb4a,
0x3f3504f3,0xbf3504f3,0x3f226799,0xbf45e403,0x3f0e39da,0xbf54db31,0x3ef15aea,0xbf61c598,0x3ec3ef15,0xbf6c835e,0x3e94a031,0xbf74fa0b,
0x3e47c5c2,0xbf7b14be,0x3dc8bd36,0xbf7ec46d,0x3ec3ef15,0xbf6c835e,0x3e78cfcc,0xbf7853f8,0x3dc8bd36,0xbf7ec46d,0xbd48fb30,0xbf7fb10f,
0xbe47c5c2,0xbf7b14be,0xbeac7cd4,0xbf710908,0xbef15aea,0xbf61c598,0xbf187fc0,0xbf4d9f02,0x0,0xbf800000,0xbe47c5c2,0xbf7b14be,
0xbec3ef15,0xbf6c835e,0xbf0e39da,0xbf54db31,0xbf3504f3,0xbf3504f3,0xbf54db31,0xbf0e39da,0xbf6c835e,0xbec3ef15,0xbf7b14be,0xbe47c5c2,
0xbec3ef15,0xbf6c835e,0xbf187fc0,0xbf4d9f02,0xbf45e403,0xbf226799,0xbf676bd8,0xbedae880,0xbf7b14be,0xbe47c5c2,0xbf7fb10f,0x3d48fb30,
0xbf74fa0b,0x3e94a031,0xbf5b941a,0x3f039c3d,0xbf3504f3,0xbf3504f3,0xbf61c598,0xbef15aea,0xbf7b14be,0xbe47c5c2,0xbf7ec46d,0x3dc8bd36,
0xbf6c835e,0x3ec3ef15,0xbf45e403,0x3f226799,0xbf0e39da,0x3f54db31,0xbe94a031,0x3f74fa0b,0xbf6c835e,0xbec3ef15,0xbf7fb10f,0xbd48fb30,
0xbf74fa0b,0x3e94a031,0xbf4d9f02,0x3f187fc0,0xbf0e39da,0x3f54db31,0xbe78cfcc,0x3f7853f8,0x3dc8bd36,0x3f7ec46d,0x3edae880,0x3f676bd8,
0x80003f80,0x3f800000,0x3f800000,0xbf80,0x3ec43f6d,0x3f6dbec4,0x3f6dbec4,0xbec4bf6d,0x3f353f35,0x3f35bf35,0x3f35bf35,0xbf35bf35,
0x3f6d3ec4,0x3ec4bf6d,0x3ec4bf6d,0xbf6dbec4,0x80003f80,0x3f800000,0xbf800000,0x3f80,0x3f6d3ec4,0x3ec4bf6d,0xbec43f6d,0x3f6d3ec4,
0x3f35bf35,0xbf35bf35,0x3f353f35,0x3f35bf35,0xbec4bf6d,0xbf6d3ec4,0x3f6dbec4,0xbec4bf6d,0x80003f80,0x3f800000,0x3f800000,0xbf80,
0x3f6dbec4,0xbec4bf6d,0xbec4bf6d,0xbf6d3ec4,0xbf35bf35,0xbf353f35,0xbf353f35,0x3f353f35,0xbec43f6d,0x3f6d3ec4,0x3f6d3ec4,0x3ec4bf6d,
0x80003f80,0x3f800000,0xbf800000,0x3f80,0x3ec4bf6d,0xbf6dbec4,0x3f6d3ec4,0x3ec4bf6d,0xbf353f35,0x3f353f35,0xbf35bf35,0xbf353f35,
0x3f6dbec4,0xbec4bf6d,0x3ec43f6d,0x3f6dbec4,0x80003f80,0x3f800000,0x3f800000,0xbf80,0xbec4bf6d,0xbf6d3ec4,0xbf6d3ec4,0x3ec43f6d,
0x3f353f35,0x3f35bf35,0x3f35bf35,0xbf35bf35,0xbf6dbec4,0xbec43f6d,0xbec43f6d,0x3f6d3ec4,0x80003f80,0x3f800000,0xbf800000,0x3f80,
0xbf6dbec4,0xbec43f6d,0x3ec4bf6d,0xbf6dbec4,0x3f35bf35,0xbf35bf35,0x3f353f35,0x3f35bf35,0x3ec43f6d,0x3f6dbec4,0xbf6d3ec4,0x3ec43f6d,
0x80003f80,0x3f800000,0x3f800000,0xbf80,0xbf6d3ec4,0x3ec43f6d,0x3ec43f6d,0x3f6dbec4,0xbf35bf35,0xbf353f35,0xbf353f35,0x3f353f35,
0x3ec4bf6d,0xbf6dbec4,0xbf6dbec4,0xbec43f6d,0x80003f80,0x3f800000,0xbf800000,0x3f80,0xbec43f6d,0x3f6d3ec4,0xbf6dbec4,0xbec43f6d,
0xbf353f35,0x3f353f35,0xbf35bf35,0xbf353f35,0xbf6d3ec4,0x3ec43f6d,0xbec4bf6d,0xbf6d3ec4,0x3f803f80,0x80008000,0x80008000,0xbf80bf80,
0x3f803f80,0x80008000,0x80008000,0xbf80bf80,0x3f803f80,0x80008000,0x80008000,0xbf80bf80,0x3f803f80,0x80008000,0x80008000,0xbf80bf80,
0x3ec43f6d,0x3f6d3ec4,0x3f6d3ec4,0xbec4bf6d,0xbf6dbec4,0x3ec43f6d,0x3ec43f6d,0x3f6d3ec4,0xbec4bf6d,0xbf6dbec4,0xbf6dbec4,0x3ec43f6d,
0x3f6d3ec4,0xbec4bf6d,0xbec4bf6d,0xbf6dbec4,0xbf353f35,0x3f353f35,0x3f353f35,0x3f35bf35,0x3f35bf35,0xbf35bf35,0xbf35bf35,0xbf353f35,
0xbf353f35,0x3f353f35,0x3f353f35,0x3f35bf35,0x3f35bf35,0xbf35bf35,0xbf35bf35,0xbf353f35,0xbf6d3ec4,0xbec43f6d,0xbec43f6d,0x3f6dbec4,
0xbec43f6d,0x3f6dbec4,0x3f6dbec4,0x3ec4bf6d,0x3f6dbec4,0x3ec4bf6d,0x3ec4bf6d,0xbf6d3ec4,0x3ec4bf6d,0xbf6d3ec4,0xbf6d3ec4,0xbec43f6d,
0x0,0xbf803f80,0xbf803f80,0x80008000,0x0,0xbf803f80,0xbf803f80,0x80008000,0x0,0xbf803f80,0xbf803f80,0x80008000,
0x0,0xbf803f80,0xbf803f80,0x80008000,0x3f6dbec4,0xbec43f6d,0xbec43f6d,0xbf6d3ec4,0x3ec4bf6d,0x3f6dbec4,0x3f6dbec4,0xbec43f6d,
0xbf6d3ec4,0x3ec4bf6d,0x3ec4bf6d,0x3f6dbec4,0xbec43f6d,0xbf6d3ec4,0xbf6d3ec4,0x3ec4bf6d,0x3f35bf35,0x3f353f35,0x3f353f35,0xbf353f35,
0xbf353f35,0xbf35bf35,0xbf35bf35,0x3f35bf35,0x3f35bf35,0x3f353f35,0x3f353f35,0xbf353f35,0xbf353f35,0xbf35bf35,0xbf35bf35,0x3f35bf35,
0xbec4bf6d,0x3f6d3ec4,0x3f6d3ec4,0x3ec43f6d,0x3f6d3ec4,0x3ec43f6d,0x3ec43f6d,0xbf6dbec4,0x3ec43f6d,0xbf6dbec4,0xbf6dbec4,0xbec4bf6d,
0xbf6dbec4,0xbec4bf6d,0xbec4bf6d,0x3f6d3ec4,0x3f800000,0x0,0x3f7fec43,0xbcc90ab0,0x3f7fb10f,0xbd48fb30,0x3f7f4e6d,0xbd96a905,
0x3f7ec46d,0xbdc8bd36,0x3f7e1324,0xbdfab273,0x3f7d3aac,0xbe164083,0x3f7c3b28,0xbe2f10a2,0x3f800000,0x0,0x3f7f4e6d,0xbd96a905,
0x3f7d3aac,0xbe164083,0x3f79c79d,0xbe605c13,0x3f74fa0b,0xbe94a031,0x3f6ed89e,0xbeb8442a,0x3f676bd8,0xbedae880,0x3f5ebe05,0xbefc5d27,
0x3f800000,0x0,0x3f7e1324,0xbdfab273,0x3f7853f8,0xbe78cfcc,0x3f6ed89e,0xbeb8442a,0x3f61c598,0xbef15aea,0x3f514d3d,0xbf13682a,
0x3f3daef9,0xbf2beb4a,0x3f273656,0xbf41d870,0x3f800000,0x0,0x3f7c3b28,0xbe2f10a2,0x3f710908,0xbeac7cd4,0x3f5ebe05,0xbefc5d27,
0x3f45e403,0xbf226799,0x3f273656,0xbf41d870,0x3f039c3d,0xbf5b941a,0x3eb8442a,0xbf6ed89e,0x3f800000,0x0,0x3f79c79d,0xbe605c13,
0x3f676bd8,0xbedae880,0x3f49d112,0xbf1d7fd1,0x3f226799,0xbf45e403,0x3ee63375,0xbf64aa59,0x3e78cfcc,0xbf7853f8,0x3cc90ab0,0xbf7fec43,
0x3f800000,0x0,0x3f76ba07,0xbe888e93,0x3f5b941a,0xbf039c3d,0x3f3085bb,0xbf396842,0x3ef15aea,0xbf61c598,0x3e605c13,0xbf79c79d,
0xbd48fb30,0xbf7fb10f,0xbea09ae5,0xbf731447,0x3f800000,0x0,0x3f731447,0xbea09ae5,0x3f4d9f02,0xbf187fc0,0x3f13682a,0xbf514d3d,
0x3e94a031,0xbf74fa0b,0xbcc90ab0,0xbf7fec43,0xbeac7cd4,0xbf710908,0xbf1d7fd1,0xbf49d112,0x3f800000,0x0,0x3f6ed89e,0xbeb8442a,
0x3f3daef9,0xbf2beb4a,0x3ee63375,0xbf64aa59,0x3dc8bd36,0xbf7ec46d,0xbe888e93,0xbf76ba07,0xbf187fc0,0xbf4d9f02,0xbf584853,0xbf08f59b,
0x3f7b14be,0xbe47c5c2,0x3f79c79d,0xbe605c13,0x3f7853f8,0xbe78cfcc,0x3f76ba07,0xbe888e93,0x3f74fa0b,0xbe94a031,0x3f731447,0xbea09ae5,
0x3f710908,0xbeac7cd4,0x3f6ed89e,0xbeb8442a,0x3f54db31,0xbf0e39da,0x3f49d112,0xbf1d7fd1,0x3f3daef9,0xbf2beb4a,0x3f3085bb,0xbf396842,
0x3f226799,0xbf45e403,0x3f13682a,0xbf514d3d,0x3f039c3d,0xbf5b941a,0x3ee63375,0xbf64aa59,0x3f0e39da,0xbf54db31,0x3ee63375,0xbf64aa59,
0x3eac7cd4,0xbf710908,0x3e605c13,0xbf79c79d,0x3dc8bd36,0xbf7ec46d,0xbcc90ab0,0xbf7fec43,0xbe164083,0xbf7d3aac,0xbe888e93,0xbf76ba07,
0x3e47c5c2,0xbf7b14be,0x3cc90ab0,0xbf7fec43,0xbe164083,0xbf7d3aac,0xbea09ae5,0xbf731447,0xbef15aea,0xbf61c598,0xbf1d7fd1,0xbf49d112,
0xbf3daef9,0xbf2beb4a,0xbf584853,0xbf08f59b,0xbe47c5c2,0xbf7b14be,0xbecf7bca,0xbf6a09a7,0xbf187fc0,0xbf4d9f02,0xbf41d870,0xbf273656,
0xbf61c598,0xbef15aea,0xbf76ba07,0xbe888e93,0xbf7fb10f,0xbd48fb30,0xbf7c3b28,0x3e2f10a2,0xbf0e39da,0xbf54db31,0xbf41d870,0xbf273656,
0xbf676bd8,0xbedae880,0xbf7c3b28,0xbe2f10a2,0xbf7ec46d,0x3dc8bd36,0xbf6ed89e,0x3eb8442a,0xbf4d9f02,0x3f187fc0,0xbf1d7fd1,0x3f49d112,
0xbf54db31,0xbf0e39da,0xbf76ba07,0xbe888e93,0xbf7fb10f,0x3d48fb30,0xbf6ed89e,0x3eb8442a,0xbf45e403,0x3f226799,0xbf08f59b,0x3f584853,
0xbe78cfcc,0x3f7853f8,0x3d96a905,0x3f7f4e6d,0xbf7b14be,0xbe47c5c2,0xbf7c3b28,0x3e2f10a2,0xbf5b941a,0x3f039c3d,0xbf1d7fd1,0x3f49d112,
0xbe94a031,0x3f74fa0b,0x3d96a905,0x3f7f4e6d,0x3edae880,0x3f676bd8,0x3f396842,0x3f3085bb,0x80003f80,0x80003f80,0x80003f80,0x80003f80,
0x80003f80,0x80003f80,0x80003f80,0x80003f80,0x80003f80,0x80003f80,0x80003f80,0x80003f80,0x80003f80,0x80003f80,0x80003f80,0x80003f80,
0x3f800000,0x3f800000,0x3f800000,0x3f800000,0x3f800000,0x3f800000,0x3f800000,0x3f800000,0x3f800000,0x3f800000,0x3f800000,0x3f800000,
0x3f800000,0x3f800000,0x3f800000,0x3f800000,0x80003f80,0x3f353f35,0x80003f80,0x3f353f35,0x3f800000,0x3f35bf35,0x3f800000,0x3f35bf35,
0x8000bf80,0xbf35bf35,0x8000bf80,0xbf35bf35,0xbf800000,0xbf353f35,0xbf800000,0xbf353f35,0x3f800000,0x3f35bf35,0x3f800000,0x3f35bf35,
0xbf80,0xbf35bf35,0xbf80,0xbf35bf35,0xbf800000,0xbf353f35,0xbf800000,0xbf353f35,0x3f80,0x3f353f35,0x3f80,0x3f353f35,
0x80003f80,0x3f800000,0x80003f80,0x3f800000,0x8000bf80,0xbf800000,0x8000bf80,0xbf800000,0x80003f80,0x3f800000,0x80003f80,0x3f800000,
0x8000bf80,0xbf800000,0x8000bf80,0xbf800000,0x3f800000,0xbf80,0x3f800000,0xbf80,0xbf800000,0x3f80,0xbf800000,0x3f80,
0x3f800000,0xbf80,0x3f800000,0xbf80,0xbf800000,0x3f80,0xbf800000,0x3f80,0x80003f80,0x3f35bf35,0x80003f80,0x3f35bf35,
0xbf800000,0x3f353f35,0xbf800000,0x3f353f35,0x8000bf80,0xbf353f35,0x8000bf80,0xbf353f35,0x3f800000,0xbf35bf35,0x3f800000,0xbf35bf35,
0x3f800000,0xbf35bf35,0x3f800000,0xbf35bf35,0x3f80,0x3f35bf35,0x3f80,0x3f35bf35,0xbf800000,0x3f353f35,0xbf800000,0x3f353f35,
0xbf80,0xbf353f35,0xbf80,0xbf353f35,0x80003f80,0x3ec43f6d,0x8000bf80,0xbec4bf6d,0x3f353f35,0x3f6d3ec4,0xbf35bf35,0xbf6dbec4,
0x3f800000,0x3f6dbec4,0xbf800000,0xbf6d3ec4,0x3f35bf35,0x3ec4bf6d,0xbf353f35,0xbec43f6d,0x3f800000,0x3f6dbec4,0xbf800000,0xbf6d3ec4,
0x3f35bf35,0x3ec4bf6d,0xbf353f35,0xbec43f6d,0xbf80,0xbec4bf6d,0x3f80,0x3ec43f6d,0xbf35bf35,0xbf6dbec4,0x3f353f35,0x3f6d3ec4,
0x80003f80,0x3f6d3ec4,0x8000bf80,0xbf6dbec4,0x3f35bf35,0xbec4bf6d,0xbf353f35,0x3ec43f6d,0xbf800000,0xbec43f6d,0x3f800000,0x3ec4bf6d,
0x3f353f35,0x3f6dbec4,0xbf35bf35,0xbf6d3ec4,0x3f800000,0x3ec4bf6d,0xbf800000,0xbec43f6d,0xbf35bf35,0xbf6d3ec4,0x3f353f35,0x3f6dbec4,
0x3f80,0x3f6d3ec4,0xbf80,0xbf6dbec4,0x3f35bf35,0xbec4bf6d,0xbf353f35,0x3ec43f6d,0x80003f80,0x3f6dbec4,0x8000bf80,0xbf6d3ec4,
0xbf35bf35,0xbec43f6d,0x3f353f35,0x3ec4bf6d,0x3f800000,0xbec4bf6d,0xbf800000,0x3ec43f6d,0xbf353f35,0x3f6d3ec4,0x3f35bf35,0xbf6dbec4,
0x3f800000,0xbec4bf6d,0xbf800000,0x3ec43f6d,0xbf353f35,0x3f6d3ec4,0x3f35bf35,0xbf6dbec4,0xbf80,0xbf6d3ec4,0x3f80,0x3f6dbec4,
0x3f353f35,0x3ec4bf6d,0xbf35bf35,0xbec43f6d,0x80003f80,0x3ec4bf6d,0x8000bf80,0xbec43f6d,0xbf353f35,0x3f6dbec4,0x3f35bf35,0xbf6d3ec4,
0xbf800000,0x3f6d3ec4,0x3f800000,0xbf6dbec4,0xbf35bf35,0x3ec43f6d,0x3f353f35,0xbec4bf6d,0x3f800000,0xbf6dbec4,0xbf800000,0x3f6d3ec4,
0x3f353f35,0xbec4bf6d,0xbf35bf35,0x3ec43f6d,0x3f80,0x3ec4bf6d,0xbf80,0xbec43f6d,0xbf353f35,0x3f6dbec4,0x3f35bf35,0xbf6d3ec4,
0x80003f80,0x8000bf80,0x80003f80,0x8000bf80,0x80003f80,0x8000bf80,0x80003f80,0x8000bf80,0x80003f80,0x8000bf80,0x80003f80,0x8000bf80,
0x80003f80,0x8000bf80,0x80003f80,0x8000bf80,0x3f800000,0xbf800000,0x3f800000,0xbf800000,0x3f800000,0xbf800000,0x3f800000,0xbf800000,
0x3f800000,0xbf800000,0x3f800000,0xbf800000,0x3f800000,0xbf800000,0x3f800000,0xbf800000,0x80003f80,0xbf35bf35,0x80003f80,0xbf35bf35,
0x3f800000,0xbf353f35,0x3f800000,0xbf353f35,0x8000bf80,0x3f353f35,0x8000bf80,0x3f353f35,0xbf800000,0x3f35bf35,0xbf800000,0x3f35bf35,
0x3f800000,0xbf353f35,0x3f800000,0xbf353f35,0xbf80,0x3f353f35,0xbf80,0x3f353f35,0xbf800000,0x3f35bf35,0xbf800000,0x3f35bf35,
0x3f80,0xbf35bf35,0x3f80,0xbf35bf35,0x80003f80,0xbf800000,0x80003f80,0xbf800000,0x8000bf80,0x3f800000,0x8000bf80,0x3f800000,
0x80003f80,0xbf800000,0x80003f80,0xbf800000,0x8000bf80,0x3f800000,0x8000bf80,0x3f800000,0x3f800000,0x3f80,0x3f800000,0x3f80,
0xbf800000,0xbf80,0xbf800000,0xbf80,0x3f800000,0x3f80,0x3f800000,0x3f80,0xbf800000,0xbf80,0xbf800000,0xbf80,
0x80003f80,0xbf353f35,0x80003f80,0xbf353f35,0xbf800000,0xbf35bf35,0xbf800000,0xbf35bf35,0x8000bf80,0x3f35bf35,0x8000bf80,0x3f35bf35,
0x3f800000,0x3f353f35,0x3f800000,0x3f353f35,0x3f800000,0x3f353f35,0x3f800000,0x3f353f35,0x3f80,0xbf353f35,0x3f80,0xbf353f35,
0xbf800000,0xbf35bf35,0xbf800000,0xbf35bf35,0xbf80,0x3f35bf35,0xbf80,0x3f35bf35,0x80003f80,0xbec4bf6d,0x8000bf80,0x3ec43f6d,
0x3f353f35,0xbf6dbec4,0xbf35bf35,0x3f6d3ec4,0x3f800000,0xbf6d3ec4,0xbf800000,0x3f6dbec4,0x3f35bf35,0xbec43f6d,0xbf353f35,0x3ec4bf6d,
0x3f800000,0xbf6d3ec4,0xbf800000,0x3f6dbec4,0x3f35bf35,0xbec43f6d,0xbf353f35,0x3ec4bf6d,0xbf80,0x3ec43f6d,0x3f80,0xbec4bf6d,
0xbf35bf35,0x3f6d3ec4,0x3f353f35,0xbf6dbec4,0x80003f80,0xbf6dbec4,0x8000bf80,0x3f6d3ec4,0x3f35bf35,0x3ec43f6d,0xbf353f35,0xbec4bf6d,
0xbf800000,0x3ec4bf6d,0x3f800000,0xbec43f6d,0x3f353f35,0xbf6d3ec4,0xbf35bf35,0x3f6dbec4,0x3f800000,0xbec43f6d,0xbf800000,0x3ec4bf6d,
0xbf35bf35,0x3f6dbec4,0x3f353f35,0xbf6d3ec4,0x3f80,0xbf6dbec4,0xbf80,0x3f6d3ec4,0x3f35bf35,0x3ec43f6d,0xbf353f35,0xbec4bf6d,
0x80003f80,0xbf6d3ec4,0x8000bf80,0x3f6dbec4,0xbf35bf35,0x3ec4bf6d,0x3f353f35,0xbec43f6d,0x3f800000,0x3ec43f6d,0xbf800000,0xbec4bf6d,
0xbf353f35,0xbf6dbec4,0x3f35bf35,0x3f6d3ec4,0x3f800000,0x3ec43f6d,0xbf800000,0xbec4bf6d,0xbf353f35,0xbf6dbec4,0x3f35bf35,0x3f6d3ec4,
0xbf80,0x3f6dbec4,0x3f80,0xbf6d3ec4,0x3f353f35,0xbec43f6d,0xbf35bf35,0x3ec4bf6d,0x80003f80,0xbec43f6d,0x8000bf80,0x3ec4bf6d,
0xbf353f35,0xbf6d3ec4,0x3f35bf35,0x3f6dbec4,0xbf800000,0xbf6dbec4,0x3f800000,0x3f6d3ec4,0xbf35bf35,0xbec4bf6d,0x3f353f35,0x3ec43f6d,
0x3f800000,0x3f6d3ec4,0xbf800000,0xbf6dbec4,0x3f353f35,0x3ec43f6d,0xbf35bf35,0xbec4bf6d,0x3f80,0xbec43f6d,0xbf80,0x3ec4bf6d,
0xbf353f35,0xbf6d3ec4,0x3f35bf35,0x3f6dbec4,
};
constexpr int TB_F = 0, TB_E = 512, TB_P2 = 1024;

enum { C_EP = 0, C_Z1 = 32, C_Z2 = 96, C_H3 = 128, C_U = 160, C_X = 288, C_TOTAL = 512 };
struct Scratch {
  unsigned cnt[C_TOTAL];
  uint32_t moda[8 * 2 * D_];
  uint32_t mod[4 * D_ + 256];
  uint32_t z1[120 * 5120];
  uint32_t z2[128 * 4800];
  uint8_t h3[32 * 18 * 4096];
  uint8_t u[72 * D_ * 128];
};
__device__ __align__(1024) Scratch g_s;

#define PF2 8
#define PF2K 16
#define HOLDA 5
#define GOAT 0
#define H3W 0
#define X1K 10
#define PEEK 1
#ifndef NV1
#define NV1 12
#endif
#ifndef NV2
#define NV2 20
#endif
#define GDEP 0
#define TRK0 50
#define W0N 3
#define TRKC 350
#define J2 6
#define HD1 200
#define STRESS 0
#define NG1 1

#define FAILCNT(k) do {} while (0)
#define CK(k) do {} while (0)
#define CKX(k) do {} while (0)
#define TS(k) do {} while (0)
#define TSC(k) do {} while (0)
struct Maps { CUtensorMap z1, z2[2], w1a, w1b, h3, w2, wf[4], wm; };
struct Params {
  const __nv_bfloat16 *x, *c, *wmod;
  Scratch* s;
  const uint4* tab;
  const __nv_bfloat16 *wr, *wi, *w1, *w2, *b1, *b2;
  uint32_t* out;
};

__device__ __forceinline__ uint32_t smem_u32(const void* p) { return (uint32_t)__cvta_generic_to_shared(p); }
__device__ __forceinline__ void mbar_init(uint32_t b, int c) { asm volatile("mbarrier.init.shared::cta.b64 [%0], %1;" ::"r"(b), "r"(c)); }
__device__ __forceinline__ void mbar_expect(uint32_t b, int bytes) { asm volatile("mbarrier.arrive.expect_tx.shared::cta.b64 _, [%0], %1;" ::"r"(b), "r"(bytes) : "memory"); }
__device__ __forceinline__ void mbar_arrive(uint32_t b) { asm volatile("mbarrier.arrive.shared::cta.b64 _, [%0];" ::"r"(b) : "memory"); }
#define MBAR_WAIT(SEM)                                                                                                         \
  asm volatile("{\n.reg .pred p;\n.reg .u32 it;\nmov.u32 it, 0;\nW:\nmbarrier.try_wait.parity" SEM ".shared::cta.b64 p, [%0], %1;\n" \
               "@p bra.uni D;\nadd.u32 it, it, 1;\nsetp.lt.u32 p, it, 0x400000;\n@p bra.uni W;\ntrap;\nD:\n}" ::"r"(b), "r"(ph) : "memory")
__device__ __forceinline__ void mbar_wait(uint32_t b, int ph) { MBAR_WAIT(""); }
__device__ __forceinline__ uint32_t mbar_test(uint32_t b, int ph) {
  uint32_t ok;
  asm volatile("{\n.reg .pred p;\nmbarrier.test_wait.parity.shared::cta.b64 p, [%1], %2;\nselp.u32 %0, 1, 0, p;\n}\n" : "=r"(ok) : "r"(b), "r"(ph) : "memory");
  return ok;
}
__device__ __forceinline__ void tma2d(uint32_t dst, const CUtensorMap* m, int c0, int c1, uint32_t bar) {
  asm volatile("cp.async.bulk.tensor.2d.shared::cluster.global.mbarrier::complete_tx::bytes [%0], [%1, {%3, %4}], [%2];" ::"r"(dst), "l"(m), "r"(bar), "r"(c0), "r"(c1) : "memory");
}
__device__ __forceinline__ uint64_t pol_ef() { uint64_t p; asm("createpolicy.fractional.L2::evict_first.b64 %0, 1.0;" : "=l"(p)); return p; }
__device__ __forceinline__ void tma3d_ef(uint32_t dst, const CUtensorMap* m, int c1, int c2, uint32_t bar) {
  asm volatile("cp.async.bulk.tensor.3d.shared::cluster.global.mbarrier::complete_tx::bytes.L2::cache_hint [%0], [%1, {%3, %4, %5}], [%2], %6;" ::"r"(dst), "l"(m), "r"(bar), "r"(0), "r"(c1), "r"(c2), "l"(pol_ef()) : "memory");
}
__device__ __forceinline__ void tma4d_ef(uint32_t dst, const CUtensorMap* m, int c1, int c2, int c3, uint32_t bar) {
  asm volatile("cp.async.bulk.tensor.4d.shared::cluster.global.mbarrier::complete_tx::bytes.L2::cache_hint [%0], [%1, {%3, %7, %4, %5}], [%2], %6;" ::"r"(dst), "l"(m), "r"(bar), "r"(0), "r"(c2), "r"(c3), "l"(pol_ef()), "r"(c1) : "memory");
}
__device__ __forceinline__ void bulk_ld(uint32_t dst, const void* src, int bytes, uint32_t bar) {
  asm volatile("cp.async.bulk.shared::cluster.global.mbarrier::complete_tx::bytes [%0], [%1], %2, [%3];" ::"r"(dst), "l"(src), "r"(bytes), "r"(bar) : "memory");
}
__device__ __forceinline__ void bulk_st(void* dst, uint32_t src, int bytes) {
  asm volatile("cp.async.bulk.global.shared::cta.bulk_group [%0], [%1], %2;" ::"l"(dst), "r"(src), "r"(bytes) : "memory");
}
__device__ __forceinline__ void tma_st2d(const CUtensorMap* m, uint32_t src, int c0, int c1) {
  asm volatile("cp.async.bulk.tensor.2d.global.shared::cta.bulk_group [%0, {%2, %3}], [%1];" ::"l"(m), "r"(src), "r"(c0), "r"(c1) : "memory");
}
__device__ __forceinline__ void tma_st3d(const CUtensorMap* m, uint32_t src, int c0, int c1, int c2) {
  asm volatile("cp.async.bulk.tensor.3d.global.shared::cta.bulk_group [%0, {%2, %3, %4}], [%1];" ::"l"(m), "r"(src), "r"(c0), "r"(c1), "r"(c2) : "memory");
}
__device__ __forceinline__ void bulk_commit_wait_read() {
  asm volatile("cp.async.bulk.commit_group;" ::: "memory");
  asm volatile("cp.async.bulk.wait_group.read 0;" ::: "memory");
}
__device__ __forceinline__ void bulk_commit_wait() {
  asm volatile("cp.async.bulk.commit_group;" ::: "memory");
  asm volatile("cp.async.bulk.wait_group 0;" ::: "memory");
}
__device__ __forceinline__ void prefetch_l2(const void* p, int bytes) {
  asm volatile("cp.async.bulk.prefetch.L2.global [%0], %1;" ::"l"(p), "r"(bytes) : "memory");
}
__device__ __forceinline__ void wg_fence() { asm volatile("wgmma.fence.sync.aligned;" ::: "memory"); }
__device__ __forceinline__ void wg_commit() { asm volatile("wgmma.commit_group.sync.aligned;" ::: "memory"); }
template <int N> __device__ __forceinline__ void wg_wait() { asm volatile("wgmma.wait_group.sync.aligned %0;" ::"n"(N) : "memory"); }
template <int N> __device__ __forceinline__ void reg_fence(float (&d)[N]) {
#pragma unroll
  for (int i = 0; i < N; i++) asm volatile("" : "+f"(d[i])::"memory");
}
__device__ __forceinline__ void fence_async_smem() { asm volatile("fence.proxy.async.shared::cta;" ::: "memory"); }
__device__ __forceinline__ void fence_async_glb() { asm volatile("fence.proxy.async.global;" ::: "memory"); }
__device__ __forceinline__ uint32_t ld_rlx(const void* p) { uint32_t v; asm volatile("ld.relaxed.gpu.global.b32 %0, [%1];" : "=r"(v) : "l"(p) : "memory"); return v; }
__device__ __forceinline__ uint2 ld_rlx2(const void* p) { uint2 v; asm volatile("ld.relaxed.gpu.global.v2.b32 {%0,%1}, [%2];" : "=r"(v.x), "=r"(v.y) : "l"(p) : "memory"); return v; }
__device__ __forceinline__ uint4 ld_rlx4(const void* p) { uint4 v; asm volatile("ld.relaxed.gpu.global.v4.b32 {%0,%1,%2,%3}, [%4];" : "=r"(v.x), "=r"(v.y), "=r"(v.z), "=r"(v.w) : "l"(p) : "memory"); return v; }
__device__ __forceinline__ uint32_t ld_nc(const void* p) { uint32_t v; asm volatile("ld.global.nc.L1::no_allocate.b32 %0, [%1];" : "=r"(v) : "l"(p) : "memory"); return v; }
__device__ __forceinline__ uint4 ld_nc4(const void* p) { uint4 v; asm volatile("ld.global.nc.v4.b32 {%0,%1,%2,%3}, [%4];" : "=r"(v.x), "=r"(v.y), "=r"(v.z), "=r"(v.w) : "l"(p) : "memory"); return v; }
__device__ __forceinline__ uint32_t lds(uint32_t a) { uint32_t v; asm volatile("ld.shared.b32 %0, [%1];" : "=r"(v) : "r"(a) : "memory"); return v; }
__device__ __forceinline__ uint2 lds2(uint32_t a) { uint2 v; asm volatile("ld.shared.v2.b32 {%0,%1}, [%2];" : "=r"(v.x), "=r"(v.y) : "r"(a) : "memory"); return v; }
__device__ __forceinline__ void lds2_if(int on, uint2& v, uint32_t a) { asm volatile("{\n.reg .pred p;\nsetp.ne.u32 p, %3, 0;\n@p ld.shared.v2.b32 {%0,%1}, [%2];\n}" : "+r"(v.x), "+r"(v.y) : "r"(a), "r"(on) : "memory"); }
__device__ __forceinline__ uint4 lds4(uint32_t a) { uint4 v; asm volatile("ld.shared.v4.b32 {%0,%1,%2,%3}, [%4];" : "=r"(v.x), "=r"(v.y), "=r"(v.z), "=r"(v.w) : "r"(a) : "memory"); return v; }
__device__ __forceinline__ float lds_bf(uint32_t a) { uint32_t v; asm volatile("ld.shared.u16 %0, [%1];" : "=r"(v) : "r"(a) : "memory"); return __uint_as_float(v << 16); }
__device__ __forceinline__ void sts(uint32_t a, uint32_t v) { asm volatile("st.shared.b32 [%0], %1;" ::"r"(a), "r"(v) : "memory"); }
__device__ __forceinline__ void sts2(uint32_t a, uint32_t v0, uint32_t v1) { asm volatile("st.shared.v2.b32 [%0], {%1,%2};" ::"r"(a), "r"(v0), "r"(v1) : "memory"); }
__device__ __forceinline__ void sts4(uint32_t a, uint32_t v0, uint32_t v1, uint32_t v2, uint32_t v3) { asm volatile("st.shared.v4.b32 [%0], {%1,%2,%3,%4};" ::"r"(a), "r"(v0), "r"(v1), "r"(v2), "r"(v3) : "memory"); }
__device__ __forceinline__ void bar_sync(int id, int n) { asm volatile("bar.sync %0, %1;" ::"r"(id), "r"(n) : "memory"); }
__device__ __forceinline__ void bar_arrive(int id, int n) { asm volatile("bar.arrive %0, %1;" ::"r"(id), "r"(n) : "memory"); }
__device__ __forceinline__ void red_add(unsigned* p, unsigned v) { asm volatile("red.relaxed.gpu.global.add.u32 [%0], %1;" ::"l"(p), "r"(v) : "memory"); }
__device__ __forceinline__ bool any(bool p) { return __any_sync(0xffffffffu, p); }
__device__ __forceinline__ void pause(unsigned clks) {
  asm volatile("{\n.reg .pred p;\n.reg .u32 a, b;\nmov.u32 a, %%clock;\nW:\nmov.u32 b, %%clock;\nsub.u32 b, b, a;\nsetp.lt.s32 p, b, %0;\n@p bra.uni W;\n}" ::"r"(clks) : "memory");
}
__device__ __forceinline__ void red_bf16x8(uint32_t* p, uint32_t a, uint32_t b, uint32_t c, uint32_t d) {
  asm volatile("red.relaxed.gpu.global.add.noftz.v4.bf16x2 [%0], {%1,%2,%3,%4};" ::"l"(p), "r"(a), "r"(b), "r"(c), "r"(d) : "memory");
}
__device__ __forceinline__ void red_bf16x4(uint32_t* p, uint32_t a, uint32_t b) {
  asm volatile("red.relaxed.gpu.global.add.noftz.v2.bf16x2 [%0], {%1,%2};" ::"l"(p), "r"(a), "r"(b) : "memory");
}
constexpr int SPIN_MAX = 1 << 20;
__device__ __forceinline__ uint32_t ld_acq(const void* p) { uint32_t v; asm volatile("ld.acquire.gpu.global.b32 %0, [%1];" : "=r"(v) : "l"(p) : "memory"); return v; }
template <bool ACQ = false> __device__ __forceinline__ void wait_cnt(const unsigned* p, unsigned target) {
  int it = 0;
  while (any((int)((ACQ ? ld_acq(p) : ld_rlx(p)) - target) < 0) && ++it < SPIN_MAX) {}
}
__device__ __forceinline__ uint32_t pack_bf16(float lo, float hi) { uint32_t r; asm("cvt.rn.bf16x2.f32 %0, %1, %2;" : "=r"(r) : "f"(hi), "f"(lo)); return r; }
__device__ __forceinline__ float bf_lo(uint32_t v) { return __uint_as_float(v << 16); }
__device__ __forceinline__ float bf_hi(uint32_t v) { return __uint_as_float(v & 0xffff0000u); }
__device__ __forceinline__ uint32_t hadd2(uint32_t a, uint32_t b) { uint32_t r; asm("add.rn.bf16x2 %0, %1, %2;" : "=r"(r) : "r"(a), "r"(b)); return r; }
__device__ __forceinline__ uint32_t hmul2(uint32_t a, uint32_t b) { uint32_t r; asm("mul.rn.bf16x2 %0, %1, %2;" : "=r"(r) : "r"(a), "r"(b)); return r; }
__device__ __forceinline__ uint32_t hfma2(uint32_t a, uint32_t b, uint32_t c) { uint32_t r; asm("fma.rn.bf16x2 %0, %1, %2, %3;" : "=r"(r) : "r"(a), "r"(b), "r"(c)); return r; }
__device__ __forceinline__ float rbf(float x) { uint32_t r; asm("cvt.rn.bf16x2.f32 %0, %1, %2;" : "=r"(r) : "f"(x), "f"(0.0f)); return __uint_as_float(r); }
__device__ __forceinline__ void stmatrix4(uint32_t a, uint32_t r0, uint32_t r1, uint32_t r2, uint32_t r3) {
  asm volatile("stmatrix.sync.aligned.m8n8.x4.shared.b16 [%0], {%1,%2,%3,%4};" ::"r"(a), "r"(r0), "r"(r1), "r"(r2), "r"(r3) : "memory");
}
__device__ __forceinline__ void stmatrix2(uint32_t a, uint32_t r0, uint32_t r1) {
  asm volatile("stmatrix.sync.aligned.m8n8.x2.shared.b16 [%0], {%1,%2};" ::"r"(a), "r"(r0), "r"(r1) : "memory");
}
__device__ __forceinline__ void stmatrix4t(uint32_t a, uint32_t r0, uint32_t r1, uint32_t r2, uint32_t r3) {
  asm volatile("stmatrix.sync.aligned.m8n8.x4.trans.shared.b16 [%0], {%1,%2,%3,%4};" ::"r"(a), "r"(r0), "r"(r1), "r"(r2), "r"(r3) : "memory");
}
__device__ __forceinline__ uint32_t movm(uint32_t a) { uint32_t r; asm("movmatrix.sync.aligned.m8n8.trans.b16 %0, %1;" : "=r"(r) : "r"(a)); return r; }
template <bool ACC> __device__ __forceinline__ void mma16(float* d, uint32_t a0, uint32_t a1, uint32_t a2, uint32_t a3, uint32_t b0, uint32_t b1) {
  if (ACC) asm("mma.sync.aligned.m16n8k16.row.col.f32.bf16.bf16.f32 {%0,%1,%2,%3}, {%4,%5,%6,%7}, {%8,%9}, {%0,%1,%2,%3};"
               : "+f"(d[0]), "+f"(d[1]), "+f"(d[2]), "+f"(d[3]) : "r"(a0), "r"(a1), "r"(a2), "r"(a3), "r"(b0), "r"(b1));
  else asm("mma.sync.aligned.m16n8k16.row.col.f32.bf16.bf16.f32 {%0,%1,%2,%3}, {%4,%5,%6,%7}, {%8,%9}, {%10,%10,%10,%10};"
           : "=f"(d[0]), "=f"(d[1]), "=f"(d[2]), "=f"(d[3]) : "r"(a0), "r"(a1), "r"(a2), "r"(a3), "r"(b0), "r"(b1), "f"(0.f));
}
__device__ __forceinline__ uint32_t pin(uint32_t v) { uint32_t r; asm volatile("shfl.sync.bfly.b32 %0, %1, 0, 31, 0xffffffff;" : "=r"(r) : "r"(v)); return r; }
template <class T> __device__ __forceinline__ T* pin(T* p) {
  const uint64_t a = reinterpret_cast<uint64_t>(p);
  return reinterpret_cast<T*>((uint64_t)pin((uint32_t)a) | ((uint64_t)pin((uint32_t)(a >> 32)) << 32));
}
__device__ __forceinline__ uint32_t upin(uint32_t v) { return __shfl_sync(0xffffffffu, v, 0); }
template <class T> __device__ __forceinline__ T* upin(T* p) {
  const uint64_t a = reinterpret_cast<uint64_t>(p);
  return reinterpret_cast<T*>((uint64_t)upin((uint32_t)a) | ((uint64_t)upin((uint32_t)(a >> 32)) << 32));
}
__device__ __forceinline__ bool elect() {
  uint32_t p;
  asm volatile("{\n.reg .pred P;\nelect.sync _|P, 0xffffffff;\nselp.u32 %0, 1, 0, P;\n}" : "=r"(p));
  return p;
}
__device__ __forceinline__ uint32_t set_tag(uint32_t w, uint32_t tag) { uint32_t r; asm("lop3.b32 %0, %1, 0xfffffffe, %2, 0xea;" : "=r"(r) : "r"(w), "r"(tag)); return r; }
__device__ __forceinline__ uint32_t bitsel(uint32_t w, uint32_t m, uint32_t o) { uint32_t r; asm("lop3.b32 %0, %1, %2, %3, 0xe2;" : "=r"(r) : "r"(w), "r"(m), "r"(o)); return r; }
__device__ __forceinline__ uint32_t or3(uint32_t a, uint32_t b, uint32_t c) { uint32_t r; asm("lop3.b32 %0, %1, %2, %3, 0xfe;" : "=r"(r) : "r"(a), "r"(b), "r"(c)); return r; }
__device__ __forceinline__ uint32_t diff2(uint32_t a, uint32_t b, uint32_t tag) { uint32_t r; asm("lop3.b32 %0, %1, %2, %3, 0x7e;" : "=r"(r) : "r"(a), "r"(b), "r"(tag)); return r; }
__device__ __forceinline__ float2 cmul(float2 a, float2 b) { return make_float2(a.x * b.x - a.y * b.y, a.x * b.y + a.y * b.x); }

template<int TB> __device__ __forceinline__ void wgmma_ss_160_0(float (&d)[96], uint32_t al, uint32_t ah, uint32_t bl, uint32_t bh) {
  asm volatile("{\n.reg .b64 da, db;\nmov.b64 da, {%80, %81};\nmov.b64 db, {%82, %83};\n"
    "wgmma.mma_async.sync.aligned.m64n160k16.f32.bf16.bf16 {%0,%1,%2,%3,%4,%5,%6,%7,%8,%9,%10,%11,%12,%13,%14,%15,%16,%17,%18,%19,%20,%21,%22,%23,%24,%25,%26,%27,%28,%29,%30,%31,%32,%33,%34,%35,%36,%37,%38,%39,%40,%41,%42,%43,%44,%45,%46,%47,%48,%49,%50,%51,%52,%53,%54,%55,%56,%57,%58,%59,%60,%61,%62,%63,%64,%65,%66,%67,%68,%69,%70,%71,%72,%73,%74,%75,%76,%77,%78,%79}, da, db, 1, 1, 1, 1, %84;\n}\n"
    : "+f"(d[0]),"+f"(d[1]),"+f"(d[2]),"+f"(d[3]),"+f"(d[4]),"+f"(d[5]),"+f"(d[6]),"+f"(d[7]),"+f"(d[8]),"+f"(d[9]),"+f"(d[10]),"+f"(d[11]),"+f"(d[12]),"+f"(d[13]),"+f"(d[14]),"+f"(d[15]),"+f"(d[16]),"+f"(d[17]),"+f"(d[18]),"+f"(d[19]),"+f"(d[20]),"+f"(d[21]),"+f"(d[22]),"+f"(d[23]),"+f"(d[24]),"+f"(d[25]),"+f"(d[26]),"+f"(d[27]),"+f"(d[28]),"+f"(d[29]),"+f"(d[30]),"+f"(d[31]),"+f"(d[32]),"+f"(d[33]),"+f"(d[34]),"+f"(d[35]),"+f"(d[36]),"+f"(d[37]),"+f"(d[38]),"+f"(d[39]),"+f"(d[40]),"+f"(d[41]),"+f"(d[42]),"+f"(d[43]),"+f"(d[44]),"+f"(d[45]),"+f"(d[46]),"+f"(d[47]),"+f"(d[48]),"+f"(d[49]),"+f"(d[50]),"+f"(d[51]),"+f"(d[52]),"+f"(d[53]),"+f"(d[54]),"+f"(d[55]),"+f"(d[56]),"+f"(d[57]),"+f"(d[58]),"+f"(d[59]),"+f"(d[60]),"+f"(d[61]),"+f"(d[62]),"+f"(d[63]),"+f"(d[64]),"+f"(d[65]),"+f"(d[66]),"+f"(d[67]),"+f"(d[68]),"+f"(d[69]),"+f"(d[70]),"+f"(d[71]),"+f"(d[72]),"+f"(d[73]),"+f"(d[74]),"+f"(d[75]),"+f"(d[76]),"+f"(d[77]),"+f"(d[78]),"+f"(d[79])
    : "r"(al), "r"(ah), "r"(bl), "r"(bh), "n"(TB));
}
template<int TB> __device__ __forceinline__ void wgmma_ss_144_0(float (&d)[96], uint32_t al, uint32_t ah, uint32_t bl, uint32_t bh) {
  asm volatile("{\n.reg .b64 da, db;\nmov.b64 da, {%72, %73};\nmov.b64 db, {%74, %75};\n"
    "wgmma.mma_async.sync.aligned.m64n144k16.f32.bf16.bf16 {%0,%1,%2,%3,%4,%5,%6,%7,%8,%9,%10,%11,%12,%13,%14,%15,%16,%17,%18,%19,%20,%21,%22,%23,%24,%25,%26,%27,%28,%29,%30,%31,%32,%33,%34,%35,%36,%37,%38,%39,%40,%41,%42,%43,%44,%45,%46,%47,%48,%49,%50,%51,%52,%53,%54,%55,%56,%57,%58,%59,%60,%61,%62,%63,%64,%65,%66,%67,%68,%69,%70,%71}, da, db, 1, 1, 1, 1, %76;\n}\n"
    : "+f"(d[0]),"+f"(d[1]),"+f"(d[2]),"+f"(d[3]),"+f"(d[4]),"+f"(d[5]),"+f"(d[6]),"+f"(d[7]),"+f"(d[8]),"+f"(d[9]),"+f"(d[10]),"+f"(d[11]),"+f"(d[12]),"+f"(d[13]),"+f"(d[14]),"+f"(d[15]),"+f"(d[16]),"+f"(d[17]),"+f"(d[18]),"+f"(d[19]),"+f"(d[20]),"+f"(d[21]),"+f"(d[22]),"+f"(d[23]),"+f"(d[24]),"+f"(d[25]),"+f"(d[26]),"+f"(d[27]),"+f"(d[28]),"+f"(d[29]),"+f"(d[30]),"+f"(d[31]),"+f"(d[32]),"+f"(d[33]),"+f"(d[34]),"+f"(d[35]),"+f"(d[36]),"+f"(d[37]),"+f"(d[38]),"+f"(d[39]),"+f"(d[40]),"+f"(d[41]),"+f"(d[42]),"+f"(d[43]),"+f"(d[44]),"+f"(d[45]),"+f"(d[46]),"+f"(d[47]),"+f"(d[48]),"+f"(d[49]),"+f"(d[50]),"+f"(d[51]),"+f"(d[52]),"+f"(d[53]),"+f"(d[54]),"+f"(d[55]),"+f"(d[56]),"+f"(d[57]),"+f"(d[58]),"+f"(d[59]),"+f"(d[60]),"+f"(d[61]),"+f"(d[62]),"+f"(d[63]),"+f"(d[64]),"+f"(d[65]),"+f"(d[66]),"+f"(d[67]),"+f"(d[68]),"+f"(d[69]),"+f"(d[70]),"+f"(d[71])
    : "r"(al), "r"(ah), "r"(bl), "r"(bh), "n"(TB));
}
template<int TB> __device__ __forceinline__ void wgmma_ss_96_0(float (&d)[96], uint32_t al, uint32_t ah, uint32_t bl, uint32_t bh) {
  asm volatile("{\n.reg .b64 da, db;\nmov.b64 da, {%48, %49};\nmov.b64 db, {%50, %51};\n"
    "wgmma.mma_async.sync.aligned.m64n96k16.f32.bf16.bf16 {%0,%1,%2,%3,%4,%5,%6,%7,%8,%9,%10,%11,%12,%13,%14,%15,%16,%17,%18,%19,%20,%21,%22,%23,%24,%25,%26,%27,%28,%29,%30,%31,%32,%33,%34,%35,%36,%37,%38,%39,%40,%41,%42,%43,%44,%45,%46,%47}, da, db, 1, 1, 1, 1, %52;\n}\n"
    : "+f"(d[0]),"+f"(d[1]),"+f"(d[2]),"+f"(d[3]),"+f"(d[4]),"+f"(d[5]),"+f"(d[6]),"+f"(d[7]),"+f"(d[8]),"+f"(d[9]),"+f"(d[10]),"+f"(d[11]),"+f"(d[12]),"+f"(d[13]),"+f"(d[14]),"+f"(d[15]),"+f"(d[16]),"+f"(d[17]),"+f"(d[18]),"+f"(d[19]),"+f"(d[20]),"+f"(d[21]),"+f"(d[22]),"+f"(d[23]),"+f"(d[24]),"+f"(d[25]),"+f"(d[26]),"+f"(d[27]),"+f"(d[28]),"+f"(d[29]),"+f"(d[30]),"+f"(d[31]),"+f"(d[32]),"+f"(d[33]),"+f"(d[34]),"+f"(d[35]),"+f"(d[36]),"+f"(d[37]),"+f"(d[38]),"+f"(d[39]),"+f"(d[40]),"+f"(d[41]),"+f"(d[42]),"+f"(d[43]),"+f"(d[44]),"+f"(d[45]),"+f"(d[46]),"+f"(d[47])
    : "r"(al), "r"(ah), "r"(bl), "r"(bh), "n"(TB));
}
template<int TB> __device__ __forceinline__ void wgmma_ss_96_48(float (&d)[96], uint32_t al, uint32_t ah, uint32_t bl, uint32_t bh) {
  asm volatile("{\n.reg .b64 da, db;\nmov.b64 da, {%48, %49};\nmov.b64 db, {%50, %51};\n"
    "wgmma.mma_async.sync.aligned.m64n96k16.f32.bf16.bf16 {%0,%1,%2,%3,%4,%5,%6,%7,%8,%9,%10,%11,%12,%13,%14,%15,%16,%17,%18,%19,%20,%21,%22,%23,%24,%25,%26,%27,%28,%29,%30,%31,%32,%33,%34,%35,%36,%37,%38,%39,%40,%41,%42,%43,%44,%45,%46,%47}, da, db, 1, 1, 1, 1, %52;\n}\n"
    : "+f"(d[48]),"+f"(d[49]),"+f"(d[50]),"+f"(d[51]),"+f"(d[52]),"+f"(d[53]),"+f"(d[54]),"+f"(d[55]),"+f"(d[56]),"+f"(d[57]),"+f"(d[58]),"+f"(d[59]),"+f"(d[60]),"+f"(d[61]),"+f"(d[62]),"+f"(d[63]),"+f"(d[64]),"+f"(d[65]),"+f"(d[66]),"+f"(d[67]),"+f"(d[68]),"+f"(d[69]),"+f"(d[70]),"+f"(d[71]),"+f"(d[72]),"+f"(d[73]),"+f"(d[74]),"+f"(d[75]),"+f"(d[76]),"+f"(d[77]),"+f"(d[78]),"+f"(d[79]),"+f"(d[80]),"+f"(d[81]),"+f"(d[82]),"+f"(d[83]),"+f"(d[84]),"+f"(d[85]),"+f"(d[86]),"+f"(d[87]),"+f"(d[88]),"+f"(d[89]),"+f"(d[90]),"+f"(d[91]),"+f"(d[92]),"+f"(d[93]),"+f"(d[94]),"+f"(d[95])
    : "r"(al), "r"(ah), "r"(bl), "r"(bh), "n"(TB));
}
__device__ __forceinline__ void wgmma_rs_72(float (&d)[36], uint32_t a0, uint32_t a1, uint32_t a2, uint32_t a3, uint32_t bl, uint32_t bh, int sd) {
  asm volatile("{\n.reg .pred p;\n.reg .b64 db;\nsetp.ne.b32 p, %42, 0;\nmov.b64 db, {%40, %41};\n"
    "wgmma.mma_async.sync.aligned.m64n72k16.f32.bf16.bf16 {%0,%1,%2,%3,%4,%5,%6,%7,%8,%9,%10,%11,%12,%13,%14,%15,%16,%17,%18,%19,%20,%21,%22,%23,%24,%25,%26,%27,%28,%29,%30,%31,%32,%33,%34,%35}, {%36,%37,%38,%39}, db, p, 1, 1, 1;\n}\n"
    : "+f"(d[0]),"+f"(d[1]),"+f"(d[2]),"+f"(d[3]),"+f"(d[4]),"+f"(d[5]),"+f"(d[6]),"+f"(d[7]),"+f"(d[8]),"+f"(d[9]),"+f"(d[10]),"+f"(d[11]),"+f"(d[12]),"+f"(d[13]),"+f"(d[14]),"+f"(d[15]),"+f"(d[16]),"+f"(d[17]),"+f"(d[18]),"+f"(d[19]),"+f"(d[20]),"+f"(d[21]),"+f"(d[22]),"+f"(d[23]),"+f"(d[24]),"+f"(d[25]),"+f"(d[26]),"+f"(d[27]),"+f"(d[28]),"+f"(d[29]),"+f"(d[30]),"+f"(d[31]),"+f"(d[32]),"+f"(d[33]),"+f"(d[34]),"+f"(d[35])
    : "r"(a0), "r"(a1), "r"(a2), "r"(a3), "r"(bl), "r"(bh), "r"(sd));
}
__device__ __forceinline__ void wgmma_rs_48(float (&d)[24], uint32_t a0, uint32_t a1, uint32_t a2, uint32_t a3, uint32_t bl, uint32_t bh, int sd) {
  asm volatile("{\n.reg .pred p;\n.reg .b64 db;\nsetp.ne.b32 p, %30, 0;\nmov.b64 db, {%28, %29};\n"
    "wgmma.mma_async.sync.aligned.m64n48k16.f32.bf16.bf16 {%0,%1,%2,%3,%4,%5,%6,%7,%8,%9,%10,%11,%12,%13,%14,%15,%16,%17,%18,%19,%20,%21,%22,%23}, {%24,%25,%26,%27}, db, p, 1, 1, 1;\n}\n"
    : "+f"(d[0]),"+f"(d[1]),"+f"(d[2]),"+f"(d[3]),"+f"(d[4]),"+f"(d[5]),"+f"(d[6]),"+f"(d[7]),"+f"(d[8]),"+f"(d[9]),"+f"(d[10]),"+f"(d[11]),"+f"(d[12]),"+f"(d[13]),"+f"(d[14]),"+f"(d[15]),"+f"(d[16]),"+f"(d[17]),"+f"(d[18]),"+f"(d[19]),"+f"(d[20]),"+f"(d[21]),"+f"(d[22]),"+f"(d[23])
    : "r"(a0), "r"(a1), "r"(a2), "r"(a3), "r"(bl), "r"(bh), "r"(sd));
}
template<int N,int OFF,int TB> __device__ __forceinline__ void wgmma_ss(float (&d)[96], uint32_t al, uint32_t ah, uint32_t bl, uint32_t bh) {
  if constexpr (N==160 && OFF==0) wgmma_ss_160_0<TB>(d, al, ah, bl, bh);
  else if constexpr (N==144 && OFF==0) wgmma_ss_144_0<TB>(d, al, ah, bl, bh);
  else if constexpr (N==96 && OFF==0) wgmma_ss_96_0<TB>(d, al, ah, bl, bh);
  else if constexpr (N==96 && OFF==48) wgmma_ss_96_48<TB>(d, al, ah, bl, bh);
}

__device__ __forceinline__ void dft3(float2& a, float2& b, float2& c) {
  const float s = 0.86602540378443864676f;
  float2 t = make_float2(b.x + c.x, b.y + c.y), d = make_float2(b.x - c.x, b.y - c.y);
  float2 m = make_float2(fmaf(-0.5f, t.x, a.x), fmaf(-0.5f, t.y, a.y));
  a = make_float2(a.x + t.x, a.y + t.y);
  b = make_float2(fmaf(s, d.y, m.x), fmaf(-s, d.x, m.y));
  c = make_float2(fmaf(-s, d.y, m.x), fmaf(s, d.x, m.y));
}
__device__ __forceinline__ void dft9(float2 (&x)[9]) {
  const float2 w1 = make_float2(0.76604444311897803520f, -0.64278760968653932632f);
  const float2 w2 = make_float2(0.17364817766693034885f, -0.98480775301220805937f);
  const float2 w4 = make_float2(-0.93969262078590838405f, -0.34202014332566873304f);
  dft3(x[0], x[3], x[6]); dft3(x[1], x[4], x[7]); dft3(x[2], x[5], x[8]);
  x[4] = cmul(x[4], w1); x[7] = cmul(x[7], w2); x[5] = cmul(x[5], w2); x[8] = cmul(x[8], w4);
  dft3(x[0], x[1], x[2]); dft3(x[3], x[4], x[5]); dft3(x[6], x[7], x[8]);
  float2 t;
  t = x[1]; x[1] = x[3]; x[3] = t;
  t = x[2]; x[2] = x[6]; x[6] = t;
  t = x[5]; x[5] = x[7]; x[7] = t;
}

__device__ __forceinline__ uint32_t* mod_ptr(Scratch* sc, int u, int t128) {
  const int i = t128 & 15;
  return u < 72 ? sc->moda + (t128 >> 4) * (2 * D_) + 16 * u + 2 * (i & 7) + (i >> 3) : sc->mod + 16 * (u - 72) + i;
}
__device__ __forceinline__ void mod_unit(Scratch* sc, int u, int t128, uint32_t sw_, uint32_t bar, int ph, uint32_t rb, uint32_t tag) {
  const int w = t128 >> 5, l = t128 & 31;
  uint32_t b[18];
#pragma unroll
  for (int i = 0; i < 18; i++) b[i] = lds(red + 512 + (72 * w + 4 * i + (l & 3)) * 4);
  const uint32_t sa = pin(sw_ + (144 * w + (l & 7) + 8 * (l >> 4)) * 32 + (((l >> 3) ^ (l >> 2)) & 1) * 16);
  const uint32_t sr = pin(rb + (l >> 2) * 16 + w * 4);
  uint32_t* const dst = pin(mod_ptr(sc, u, t128));
  const int kind = u / 36;
  const float mul = __uint_as_float(pin(__float_as_uint(kind == 0 ? 16.0f : 1.0f))), add = __uint_as_float(pin(__float_as_uint(kind == 1 || kind == 4 ? 1.0f : 0.0f)));
  mbar_wait(bar, ph);
  if (t128 == 0 && u < 72) TS(10);
  float d[3][4];
#pragma unroll
  for (int i = 0; i < 9; i++) {
    uint32_t a0, a1, a2, a3;
    asm volatile("ldmatrix.sync.aligned.m8n8.x4.trans.shared.b16 {%0,%1,%2,%3}, [%4];" : "=r"(a0), "=r"(a1), "=r"(a2), "=r"(a3) : "r"(sa + i * 512) : "memory");
    if (i < 3) mma16<false>(d[i], a0, a1, a2, a3, b[2 * i], b[2 * i + 1]);
    else mma16<true>(d[i % 3], a0, a1, a2, a3, b[2 * i], b[2 * i + 1]);
  }
  if ((l & 3) == 0) { sts(sr, __float_as_uint(d[0][0] + d[1][0] + d[2][0])); sts(sr + 128, __float_as_uint(d[0][2] + d[1][2] + d[2][2])); }
  bar_sync(4, 128);
  const uint4 v = lds4(rb + (l & 15) * 16);
  const float m = rbf(fmaf(rbf((__uint_as_float(v.x) + __uint_as_float(v.y)) + (__uint_as_float(v.z) + __uint_as_float(v.w))), mul, add));
  if (u < 72 || t128 < 16) *dst = __float_as_uint(m) | tag;
}

__device__ __forceinline__ float rsq(float x) { float r; asm("rsqrt.approx.ftz.f32 %0, %1;" : "=f"(r) : "f"(x)); return r; }
__device__ __forceinline__ void ln_stats2(const float (&a)[18], const float (&b)[18], float sc, float& oa, float& ra, float& ob, float& rb) {
  float v[4] = {0.f, 0.f, 0.f, 0.f}, w[4] = {0.f, 0.f, 0.f, 0.f};
#pragma unroll
  for (int i = 0; i < 18; i += 2) {
    v[0] += a[i]; v[1] = fmaf(a[i], a[i], v[1]); v[2] += b[i]; v[3] = fmaf(b[i], b[i], v[3]);
    w[0] += a[i + 1]; w[1] = fmaf(a[i + 1], a[i + 1], w[1]); w[2] += b[i + 1]; w[3] = fmaf(b[i + 1], b[i + 1], w[3]);
  }
#pragma unroll
  for (int e = 0; e < 4; e++) v[e] += w[e];
#pragma unroll
  for (int o = 16; o; o >>= 1) {
#pragma unroll
    for (int e = 0; e < 4; e++) v[e] += __shfl_xor_sync(0xffffffffu, v[e], o);
  }
  const float ma = v[0] * (1.0f / D_), mb = v[2] * (1.0f / D_);
  ra = sc * rsq(fmaxf(fmaf(-ma, ma, v[1] * (1.0f / D_)), 0.f) + 1e-5f);
  rb = sc * rsq(fmaxf(fmaf(-mb, mb, v[3] * (1.0f / D_)), 0.f) + 1e-5f);
  oa = -ma * ra; ob = -mb * rb;
}

__device__ __forceinline__ void ln_stats1(const float (&a)[18], float sc, float& oa, float& ra) {
  float v[3] = {a[0], a[1], a[2]}, w[3] = {a[0] * a[0], a[1] * a[1], a[2] * a[2]};
#pragma unroll
  for (int i = 3; i < 18; i++) { v[i % 3] += a[i]; w[i % 3] = fmaf(a[i], a[i], w[i % 3]); }
  float s = v[0] + v[1] + v[2], q = w[0] + w[1] + w[2];
#pragma unroll
  for (int o = 16; o; o >>= 1) { s += __shfl_xor_sync(0xffffffffu, s, o); q += __shfl_xor_sync(0xffffffffu, q, o); }
  const float m = s * (1.0f / D_);
  ra = sc * rsq(fmaxf(fmaf(-m, m, q * (1.0f / D_)), 0.f) + 1e-5f);
  oa = -m * ra;
}

__device__ __forceinline__ float tmat(int c, int q, int j) {
  const int ph = q == 1 ? 1024 * j : (q >> 1) * (c + 128 * j) + 512 * (q & 1);
  return __cosf((float)(((ph + 1024) & 2047) - 1024) * (6.283185307179586f / 2048.0f));
}
__device__ __forceinline__ uint32_t line_off(int k1, int kap, int pi, int f) {
  int kd = 64 * k1 + 9 * kap;
  if (kap == 0 && k1 > 4) kd -= 288;
  if (kd >= D_) kd -= D_;
  return pi * 2400 + ((min(kd, D_ - kd) ^ f) << 3);
}

constexpr int JSK = 5;
struct Ring { uint32_t st, ph; };
template <bool G2, class T> __device__ __forceinline__ void ring_next(T& st, T& ph) {
  if (++st == NST) st = 0;
  ph ^= ((G2 ? 0xDu : 0x1u) >> st) & 1;
}
__device__ __forceinline__ void arrive_if(uint32_t a, uint32_t p) {
  asm volatile("{\n.reg .pred p;\nsetp.ne.u32 p, %1, 0;\n@p mbarrier.arrive.shared::cta.b64 _, [%0];\n}" ::"r"(a), "r"(p) : "memory");
}
template <int NA> __device__ __forceinline__ void reg_fence_n(float (&d)[96]) {
#pragma unroll
  for (int i = 0; i < NA; i++) asm volatile("" : "+f"(d[i])::"memory");
}
template <int MODE>
__device__ __forceinline__ void gemm_main(float (&acc)[96], uint32_t da0, uint32_t da1, uint32_t db0, int wg, Ring& rg,
                                          bool rows, uint32_t* x1p, const uint32_t (&xr)[18]) {
  static_assert(JSK == NST - 1, "the held slot is the first one that is not refilled by GEMM1");
  constexpr int NKB = MODE == 3 ? 36 : 32, J = MODE == 3 ? J2 : JSK;
  constexpr uint32_t HA = 0x40000040u, HB = MODE == 3 ? 0x40000040u : 0x80000020u;
  constexpr uint32_t KA = 2048 >> 4, KB = MODE == 3 ? (32 >> 4) : (1024 >> 4);
  constexpr int NA = MODE == 3 ? 72 : MODE == 1 ? 96 : 80;
  const uint32_t t = threadIdx.x & 127;
  const uint32_t eb = full0 + 8 * NST;
  uint32_t pb = 0, rel = t == 0, prel = 0, ok = 0;
  int n = MODE == 3 ? NKB - J : X1K + 2 * wg;
#pragma unroll 1
  for (int pass = MODE == 3 ? 0 : -1;; pass++) {
#pragma unroll 1
    do {
      const uint32_t so = rg.st * ((MODE == 3 ? STAGE2 : STAGE) >> 4), cb = eb + 8 * rg.st;
      if (__builtin_expect(!ok, 0)) mbar_wait(full0 + 8 * rg.st, rg.ph);
      reg_fence_n<NA>(acc);
      if (MODE == 1 && wg) {
        wg_fence();
#pragma unroll
        for (int k = 0; k < 4; k++) wgmma_ss<96, 48, 1>(acc, da1 + so + k * KA, HA, db0 + so + k * KB, HB);
        wg_commit();
      }
      wg_fence();
#pragma unroll
      for (int k = 0; k < 4; k++) {
        if (k == 3) { ring_next<MODE == 3>(rg.st, rg.ph); ok = PEEK ? mbar_test(full0 + 8 * rg.st, rg.ph) : 0; }
        if (MODE == 0) wgmma_ss<160, 0, 1>(acc, da0 + so + k * KA, HA, db0 + so + k * KB, HB);
        else if (MODE == 3) wgmma_ss<144, 0, 0>(acc, da0 + so + k * KA, HA, db0 + so + k * KB, HB);
        else wgmma_ss<96, 0, 1>(acc, da0 + so + k * KA, HA, db0 + so + k * KB, HB);
      }
      wg_commit();
      wg_wait<1>();
      reg_fence_n<NA>(acc);
      arrive_if(pb, prel);
      pb = cb; prel = rel;
    } while (--n);
    if (pass == 2 - wg) break;
    if (MODE != 3 && pass < 0) {
      if (rows) {
#pragma unroll
        for (int i = 0; i < 9; i++) { x1p[32 * i] = xr[i]; x1p[512 * 288 + 32 * i] = xr[9 + i]; }
      }
      n = NKB - JSK - X1K - 2 * wg;
      continue;
    }
    n = 1;
    if (pass == 0) {
      if (MODE != 3) prel = rel & wg;
      else { rel = 0; if (J < NST) prel = 0; }
      n = J - 1 + wg;
      if (!wg) continue;
      wg_wait<0>();
      arrive_if(pb, prel);
      prel = 0;
    }
    bar_sync(1, 256);
  }
  wg_wait<0>();
  reg_fence_n<NA>(acc);
  if (MODE != 3) arrive_if(pb, MODE == 1 ? prel & ~wg : prel);
}

constexpr float GK1 = 2.0f * 0.7978845608028654f, GK3 = 8.0f * 0.044715f * 0.7978845608028654f;

__device__ __forceinline__ int kb2_order(int i) { const int wv = i / 6; return 6 * (i - 6 * wv) + ((0x431250 >> (4 * wv)) & 7); }

__device__ __forceinline__ int kb2_pos(int kb) { const int hf = kb >= 36, k = kb - 36 * hf, gr = k / 6; return 64 * hf + gr + 6 * ((0x154230 >> (4 * (k - 6 * gr))) & 7); }

__device__ __forceinline__ void wait_flags(const unsigned* p, int idx, unsigned target, uint32_t& ready) {
  int it = 0;
  while (!((ready >> idx) & 1) && it++ < SPIN_MAX) ready = __ballot_sync(0xffffffffu, (int)(ld_rlx(p) - target) >= 0);
}

enum { B_FULL = 0, B_EMPTY = 6, B_S4 = 12, B_S5, B_LAND, B_FLT = B_LAND + 6, B_Z1, B_Z2, B_GO, B_X, B_WM, B_NUM, B_W0 = B_NUM };

__global__ void __launch_bounds__(NTHR, 1)
fused_kernel(const Params p, const __grid_constant__ Maps maps) {
  extern __shared__ __align__(1024) uint8_t smem_raw[];
  const int bx = blockIdx.x, cta = bx < 112 || bx >= 130 ? bx : bx < 114 ? bx + 16 : bx - 2;
  const int tid = threadIdx.x, t128 = tid & 127;
  const int wp = __shfl_sync(0xffffffffu, tid >> 5, 0), wg = wp >> 2;
  const int l = tid & 31, g = l >> 2, t = l & 3;
  Scratch* const sc = p.s;
  const bool rows = cta < 128;
  const int mu = rows ? cta + 4 : cta - 128;
  const int R = mu - 12;

  uint32_t xr[18];
  uint32_t cv[3];
  const unsigned ep0 = ld_rlx(&sc->cnt[C_EP + l]);
  if (tid == 0) TS(0);
  if (wg == 2) {
#pragma unroll
    for (int i = 0; i < 3; i++) cv[i] = ld_nc(reinterpret_cast<const uint32_t*>(p.c) + min(t128 + 128 * i, 287));
    if (wp == 9 && l < 9 && rows) {
      const int h = 9 * cta + l;
      prefetch_l2(reinterpret_cast<const uint8_t*>(p.wmod) + (size_t)(h >> 1) * (12 * D_) + (h & 1) * (2 * D_), 2 * D_);
    }
    if (tid == 256 && mu < 72) {
      mbar_init(full0 + 8 * B_W0, 1);
      fence_async_smem();
      mbar_expect(full0 + 8 * B_W0, 18432);
#pragma unroll 1
      for (int i = 0; i < 3; i++) tma2d(sbase + O_P2 + i * 6144, &maps.wm, 16 * mu, 192 * i, full0 + 8 * B_W0);
    }
    __syncwarp();
#pragma unroll 1
    for (int u = mu < 72 ? mu : 72 + mu; u < 216; u += u < 72 ? 72 : NCTA) if (u < 72 || t128 < 16) *mod_ptr(sc, u, t128) = 0;
    if (wp == 11 && smem_u32(smem_raw) != sbase) __trap();
    if (wp >= 10 && elect()) {
#pragma unroll 1
      for (int i = wp - 10; i < B_NUM; i += 2) mbar_init(full0 + 8 * i, i == B_FLT ? 4 : i == B_WM ? 3 : i < B_LAND && i != B_S4 ? 2 : 1);
      fence_async_smem();
    }
    __syncwarp();
  } else if (rows) {
    const uint32_t* xs = reinterpret_cast<const uint32_t*>(p.x) + (size_t)(cta + 128 * ((wp & 3) + 8 * wg)) * 288 + l;
#pragma unroll
    for (int i = 0; i < 9; i++) { xr[i] = ld_nc(xs + 32 * i); xr[9 + i] = ld_nc(xs + 512 * 288 + 32 * i); }
  }
  CK(0);
  if (tid == 64 && cta == NCTA - 1) prefetch_l2(p.tab, sizeof(T_TAB));
  __syncwarp();
  auto tag_of = [](unsigned e) { return (e & 0x7fffu) | 0x8000u; };
  const int kap = 8 * ((wp & 3) ^ (wg & 1)) + g;
  uint32_t tb[4], sb1[3], lo[9];
#pragma unroll
  for (int i = 0; i < 4; i++) tb[i] = pin(pack_bf16(tmat(cta, 8 * (i >> 1) + g, t + 8 * (i & 1)), tmat(cta, 8 * (i >> 1) + g, t + 8 * (i & 1) + 4)));
#pragma unroll
  for (int i = 0; i < 3; i++) {
    const int d = 48 * wp + 16 * i + (l & 15);
    sb1[i] = pin(sbase + O_B1 + (l >> 4) * 9216 + (d % 9) * 1024 + (d & 63) * 16);
  }
#pragma unroll
  for (int k1 = 0; k1 < 9; k1++) lo[k1] = pin(sbase + O_Z1 + line_off(k1, kap, 4 * wg + t, cta & 3));
  const uint32_t snt = pin(sbase + O_NRM + ((l & 7) + 8 * (l >> 4)) * 1168 + (48 * wp + (l & 8)) * 2), sn = pin(sbase + O_NRM + wp * 2336 + l * 4);
  const uint32_t smask = pin(t ? 0u : 0xffff0000u);
  const uint32_t* const mp = pin(sc->moda + (cta >> 4) * (2 * D_) + 48 * wp + 2 * g);
  const uint4* const ftab = pin(p.tab + TB_F + (t128 ^ (wg << 5)));

  if (wg == 2) {
#pragma unroll
    for (int i = 0; i < 3; i++) {
      const float c0 = bf_lo(cv[i]), c1 = bf_hi(cv[i]);
      sts(red + 512 + min(t128 + 128 * i, 287) * 4, pack_bf16(__fdividef(c0, 1.0f + __expf(-c0)), __fdividef(c1, 1.0f + __expf(-c1))));
    }
    if (t128 == 0) sts(full0 + 248, ep0 + 1);
    if (wp == 9 && l < 11) asm volatile("prefetch.tensormap [%0];" ::"l"(&maps.z1 + l) : "memory");
    bar_sync(4, 128);
    if (mu < 72) {
      mod_unit(sc, mu, t128, sbase + O_P2, full0 + 8 * B_W0, 0, red, tag_of(upin(ep0) + 1));
      if (t128 == 0) TS(25);
    }
    CK(1);
  }
  const int pi = R / 15, col0 = 20 * (R - 15 * pi);
  const int xu = DF_ * pi + col0, xv = DF_ * (pi ? 16 - pi : 8) + col0;
  auto load_filter = [&](int a) {
    const int x = (a & 1) ? xv : xu;
    const bool wide = (x & 15) > 12;
    mbar_expect(full0 + 8 * B_FLT, wide ? 12288 : 8192);
    tma2d(sbase + O_RAW + a * 12288, &maps.wf[a & 2], x & ~15, 0, full0 + 8 * B_FLT);
    if (wide) tma2d(sbase + O_RAW + a * 12288 + 8192, &maps.wf[(a & 2) + 1], (x & ~15) + 32, 0, full0 + 8 * B_FLT);
  };
  uint4 af[4];
  if (rows) {
    uint2 ms[3], mc[3];
    auto load_mod = [&](uint32_t o = 0) {
#pragma unroll
      for (int i = 0; i < 3; i++) { ms[i] = ld_rlx2(mp + 2 * o + 16 * i); mc[i] = ld_rlx2(mp + 2 * o + D_ + 16 * i); }
    };
    if (wg < 2) {
      float a[18], b[18];
#pragma unroll
      for (int i = 0; i < 9; i++) { a[2 * i] = bf_lo(xr[i]); a[2 * i + 1] = bf_hi(xr[i]); b[2 * i] = bf_lo(xr[9 + i]); b[2 * i + 1] = bf_hi(xr[9 + i]); }
      float oa, ra, ob, rb;
      ln_stats2(a, b, 1.0f, oa, ra, ob, rb);
      CK(1);
      load_mod((__float_as_uint(ra) | __float_as_uint(rb)) >> 31);
#pragma unroll
      for (int i = 0; i < 9; i++) {
        sts(sn + i * 128, pack_bf16(fmaf(a[2 * i], ra, oa), fmaf(a[2 * i + 1], ra, oa)));
        sts(sn + 1168 + i * 128, pack_bf16(fmaf(b[2 * i], rb, ob), fmaf(b[2 * i + 1], rb, ob)));
      }
      CK(2);
      bar_arrive(10, NTHR);
#pragma unroll
      for (int kk = 0; kk < 4; kk++) af[kk] = ld_nc4(ftab + kk * 128);
      bar_sync(1, 256);
      if (tid == 0) TS(2);
    } else {
      bar_sync(10, NTHR);
      load_mod();
      CK(2);
      if (wp >= 10 && elect()) prefetch_l2(reinterpret_cast<const uint8_t*>(wp == 10 ? p.wr : p.wi) + cta * 9248, 9248);
      __syncwarp();
    }
    float rs[3][8];
#pragma unroll
    for (int i = 0; i < 3; i++) {
      uint32_t a0, a1, a2, a3;
      asm volatile("ldmatrix.sync.aligned.m8n8.x4.trans.shared.b16 {%0,%1,%2,%3}, [%4];" : "=r"(a0), "=r"(a1), "=r"(a2), "=r"(a3)
                   : "r"(snt + 32 * i) : "memory");
      mma16<false>(&rs[i][0], a0, a1, a2, a3, tb[0], tb[1]);
      mma16<false>(&rs[i][4], a0, a1, a2, a3, tb[2], tb[3]);
    }
    CK(3);
    const uint32_t tag16 = tag_of(upin(ep0) + 1), tag1 = tag16 & 1;
    {
      int it = 0;
#pragma unroll 1
      while (true) {
        uint32_t bad = 0;
#pragma unroll
        for (int i = 0; i < 3; i++) bad |= diff2(ms[i].x, ms[i].y, tag16) | diff2(mc[i].x, mc[i].y, tag16);
        if (!any(bad & 0xffffu) || ++it > SPIN_MAX) break;
        load_mod();
      }
      CK(4);
      if (tid == 0) TS(3);
#pragma unroll
      for (int i = 0; i < 3; i++) {
        const float c0 = bf_hi(mc[i].x), c1 = bf_hi(mc[i].y);
        const float s0 = __uint_as_float(ms[i].x & smask), s1 = __uint_as_float(ms[i].y & smask);
        stmatrix4(sb1[i], pack_bf16(fmaf(rs[i][0], c0, s0), rs[i][1] * c0), pack_bf16(fmaf(rs[i][2], c1, s1), rs[i][3] * c1),
                  pack_bf16(rs[i][4] * c0, rs[i][5] * c0), pack_bf16(rs[i][6] * c1, rs[i][7] * c1));
      }
    }
    fence_async_smem();
    CK(5);
    if (wg == 2) {
      bar_arrive(5, NTHR);
      if (R >= 0 && elect()) load_filter(wp - 8);
      __syncwarp();
      const int slot = 4 * (cta & 7) + ((cta >> 4) & 3) + 32 * (2 * (cta >> 6) + ((cta >> 3) & 1));
      const uint32_t c0 = upin(40 * slot), c1 = upin(60 * (wp & 1)), src = upin(sbase + O_Z1 + (wp & 1) * 9600);
      const CUtensorMap* mz = upin(&maps.z1);
      unsigned* hint = pin(sc->cnt + C_Z1 + 32 * (wp & 1));
      if (wp < 10) {
        bar_sync(2 + (wp & 1), 160);
        if (elect()) tma_st2d(mz, src, c0, c1);
        pause(HD1);
        if (elect()) red_add(hint, 1);
        bulk_commit_wait();
        if (tid == 256) TS(4);
        __syncwarp();
      }
    } else {
      bar_sync(5, NTHR);
      CK(6);
      float acc[36];
      const uint32_t db = (((sbase + O_B1 + wg * 9216) & 0x3FFFF) >> 4) | ((128 >> 4) << 16);
      wg_fence();
#pragma unroll
      for (int kk = 0; kk < 4; kk++) wgmma_rs_72(acc, af[kk].x, af[kk].y, af[kk].z, af[kk].w, db + kk * 16, 1024 >> 4, kk);
      wg_commit();
      wg_wait<0>();
      reg_fence(acc);
      CK(7);
      float2 za[9], zb[9];
#pragma unroll
      for (int i = 0; i < 9; i++) { za[i] = make_float2(acc[4 * i], acc[4 * i + 2]); zb[i] = make_float2(acc[4 * i + 1], acc[4 * i + 3]); }
      dft9(za); dft9(zb);
      if ((wp & 3) == wg) {
        const float sp = g ? 0.f : 1.f;
#pragma unroll
        for (int k = 1; k < 5; k++) {
          float2 a = za[k], b = za[9 - k];
          za[k] = make_float2(fmaf(sp, b.x, a.x), fmaf(-sp, b.y, a.y)); za[9 - k] = make_float2(fmaf(-sp, a.x, b.x), fmaf(sp, a.y, b.y));
          a = zb[k]; b = zb[9 - k];
          zb[k] = make_float2(fmaf(sp, b.x, a.x), fmaf(-sp, b.y, a.y)); zb[9 - k] = make_float2(fmaf(-sp, a.x, b.x), fmaf(sp, a.y, b.y));
        }
        const uint32_t w0 = set_tag(pack_bf16(za[0].y, 0.f), tag1), w1 = pack_bf16(zb[0].y, 0.f);
        asm volatile("{\n.reg .pred p;\nsetp.eq.u32 p, %3, 0;\n@p st.shared.v2.b32 [%0], {%1,%2};\n}" ::"r"(lo[0] + 288 * 8), "r"(w0), "r"(w1), "r"(g) : "memory");
        za[0].y = g ? za[0].y : 0.f; zb[0].y = g ? zb[0].y : 0.f;
      }
#pragma unroll
      for (int k1 = 0; k1 < 9; k1++) sts2(lo[k1], set_tag(pack_bf16(za[k1].x, za[k1].y), tag1), pack_bf16(zb[k1].x, zb[k1].y));
      fence_async_smem();
      CK(8);
      bar_arrive(2 + wg, 160);
      {
        const uint32_t fx = (((cta >> 4) ^ cta) & 3) << 3, dl = O_IN - O_Z1, st = sbase + O_ST + 15360 + tid * 16;
        sts4(st, (lo[0] ^ fx) + dl, (lo[1] ^ fx) + dl, (lo[2] ^ fx) + dl, (lo[3] ^ fx) + dl);
        sts4(st + 4096, (lo[4] ^ fx) + dl, (lo[5] ^ fx) + dl, (lo[6] ^ fx) + dl, (lo[7] ^ fx) + dl);
        sts4(st + 8192, (lo[8] ^ fx) + dl, (lo[0] ^ fx) + dl + (kap ? 0 : 288 * 8),
             sbase + O_B3 + wg * 1024 + (l >> 4) * 2048 + (2 * (kap & 24) + (l & 15)) * 16, 0);
      }
    }
    {
      uint32_t sy[6];
#pragma unroll
      for (int i = 0; i < 6; i++) {
        const int rr = 16 * (wp & 3) + g + 8 * (i & 1);
        sy[i] = sbase + O_Y + (t * 584 + 64 * ((3 * wg + (i >> 1) + 63 - rr) % 9) + rr) * 4;
      }
      sts4(sbase + O_ST + tid * 16, movm(tb[0]), movm(tb[2]), movm(tb[1]), movm(tb[3]));
      sts4(sbase + O_ST + 6144 + tid * 16, sy[0], sy[1], sy[2], sy[3]);
      sts2(sbase + O_ST + 12288 + tid * 8, sy[4], sy[5]);
    }
  } else {
    __syncthreads();
  }

  const unsigned ep = upin(lds(full0 + 248));
  const uint32_t tag16 = tag_of(ep), tag1 = ep & 1;
  auto load_wm = [&](int u) {
    if (wp > 8 && elect()) {
      mbar_expect(full0 + 8 * B_WM, 6144);
      tma2d(sbase + O_NRM + (wp - 9) * 6144, &maps.wm, 16 * u, 192 * (wp - 9), full0 + 8 * B_WM);
    }
    __syncwarp();
  };
  if (R >= 0) {
    const int nl = (col0 + wp < DF_) + (wg < 2 && col0 + wp + 12 < DF_);
    uint4 cf[2][4], G[4];
#pragma unroll
    for (int i = 0; i < 4; i++) {
      cf[0][i] = __ldg(p.tab + TB_P2 + i * 32 + l);
      cf[1][i] = __ldg(p.tab + TB_P2 + (pi ? i : 4 + i) * 32 + l);
      G[i] = __ldg(p.tab + TB_P2 + (8 + i) * 32 + l);
    }
    const uint32_t* zin = sc->z1 + (size_t)R * 5120;
    if (wp == 10) {
      const uint32_t* zu = upin(zin);
      if (elect()) mbar_expect(full0 + 8 * B_Z1, 20480);
      wait_cnt(sc->cnt + C_Z1 + 32 * (pi >> 2), 128 * ep - 40 * STRESS);
      if (elect()) {
        bulk_ld(sbase + O_P2, zu, 20480, full0 + 8 * B_Z1);
        TS(12);
      }
      __syncwarp();
    }
    mbar_wait(full0 + 8 * B_FLT, 0);
    CK(9);
    float wn[16], wc[16];
#pragma unroll 1
    for (int ln = nl - 1; ln >= 0; ln--) {
      const int col = col0 + wp + 12 * ln, k2 = (57 * col) & 63;
      const bool cj = k2 > 32;
      const float nr = ((col & 31) == 0 && col != 0 && col != 288 ? 0.5f : 1.0f) / ((float)S_ * D_), ni = cj ? -nr : nr;
#pragma unroll
      for (int i = 0; i < 16; i++) wn[i] = wc[i];
#pragma unroll
      for (int cl = 0; cl < 2; cl++) {
        const int v = cl ^ (cj && pi), e = ((v ? xv : xu) & 15) + wp + 12 * ln, sh = e < 32 ? 6 : 5;
        const uint32_t base = sbase + O_RAW + v * 12288 + (e < 32 ? 2 * e : 8192 - 64 + 2 * e), msk = e < 32 ? 0x30 : 0x10;
        const int dm = v ? (cj || pi ? -1 : 0) : 0;
#pragma unroll
        for (int tt = 0; tt < 4; tt++) {
          const int kc = g + 64 * (tt >> 1) + 16 * t + 8 * (tt & 1);
          uint32_t a = base + ((((cj ? -kc : kc) + dm) & 127) << sh);
          a ^= (a >> 3) & msk;
          wc[4 * tt + 2 * cl] = lds_bf(a) * nr; wc[4 * tt + 2 * cl + 1] = lds_bf(a + 24576) * ni;
        }
      }
    }
    const float al = __uint_as_float(pin((pi ? 0x3f800000u : 0u) + (l >> 5)));
    const uint32_t tagv = pin(tag1 + (l >> 5));
    CK(10);
    uint32_t off = pin(l * 160 + ((wp ^ (g & 3)) << 3));
    uint32_t offo = pin(sbase + O_P2 + 20480 + off - 64 * l), po = 3072;
    unsigned* hz2 = pin(sc->cnt + C_Z2);
    const uint32_t do2 = pin(12288 - 32 * l);
    const CUtensorMap* mz2 = upin(&maps.z2[wp == 0]);
    const uint32_t sz2 = upin(sbase + O_P2 + 20480 + (wp ? 0 : 12288)), cz2 = upin(40 * R + (wp ? 0 : 24));
    mbar_wait(full0 + 8 * B_Z1, 0);
    CK(11);
    if (tid == 0) TS(8);
    if (wg == 2) load_wm(72 + mu);
    uint2 v[4], v2[4];
    const uint32_t o2 = nl > 1 ? 96 : 0;
#pragma unroll
    for (int i = 0; i < 4; i++) { v[i] = lds2(sbase + O_P2 + off + i * 5120); v2[i] = lds2(sbase + O_P2 + off + o2 + i * 5120); }
    auto bad2 = [&]() {
      return any(or3(or3(diff2(v[0].x, v[1].x, tagv), diff2(v[2].x, v[3].x, tagv), diff2(v2[0].x, v2[1].x, tagv)), diff2(v2[2].x, v2[3].x, tagv), 0) & 1);
    };
    if (__builtin_expect(bad2() && nl, 0)) {
      FAILCNT(0);
      int it = 0;
      do {
#pragma unroll
        for (int i = 0; i < 4; i++) {
          v[i] = ld_rlx2(reinterpret_cast<const uint8_t*>(zin) + off + i * 5120);
          v2[i] = ld_rlx2(reinterpret_cast<const uint8_t*>(zin) + off + o2 + i * 5120);
        }
      } while (bad2() && ++it < SPIN_MAX);
    }
#pragma unroll 1
    for (int ln = 0; ln < nl; ln++, offo += do2, po = 2048) {
      float d[4][4];
      uint32_t A[8];
#pragma unroll
      for (int h = 0; h < 2; h++) {
        mma16<false>(d[2 * h], cf[0][0].x, cf[0][0].y, cf[0][0].z, cf[0][0].w, v[h].x, v[2 + h].x);
        mma16<false>(d[2 * h + 1], cf[1][0].x, cf[1][0].y, cf[1][0].z, cf[1][0].w, v[h].y, v[2 + h].y);
      }
      if (ln) { fence_async_smem(); bar_arrive(15, NTHR); }
#pragma unroll
      for (int h = 0; h < 2; h++)
#pragma unroll
        for (int L = 0; L < 2; L++) {
          const uint4 tw = cf[L][2 + h];
          const float* z = d[2 * h + L];
          const float2 z0 = cmul(make_float2(z[0], z[2]), make_float2(__uint_as_float(tw.x), __uint_as_float(tw.y)));
          const float2 z1 = cmul(make_float2(z[1], z[3]), make_float2(__uint_as_float(tw.z), __uint_as_float(tw.w)));
          A[4 * h + L] = pack_bf16(z0.x, z0.y); A[4 * h + 2 + L] = pack_bf16(z1.x, z1.y);
        }
#pragma unroll
      for (int tt = 0; tt < 4; tt++) {
        mma16<false>(d[tt], A[0], A[1], A[2], A[3], G[tt].x, G[tt].y);
        mma16<true>(d[tt], A[4], A[5], A[6], A[7], G[tt].z, G[tt].w);
      }
#pragma unroll
      for (int tt = 0; tt < 4; tt++) {
        const float ar = d[tt][0], aj = d[tt][1], br = d[tt][2], bj = d[tt][3];
        const float2 y1 = cmul(make_float2(fmaf(-al, bj, ar), fmaf(al, br, aj)), make_float2(wc[4 * tt], wc[4 * tt + 1]));
        const float2 y2 = cmul(make_float2(fmaf(al, ar, bj), fmaf(al, aj, -br)), make_float2(wc[4 * tt + 2], wc[4 * tt + 3]));
        A[2 * tt] = pack_bf16(fmaf(al, y2.x, y1.x), fmaf(-al, y2.y, -y1.y));
        A[2 * tt + 1] = pack_bf16(fmaf(al, y1.y, -y2.y), fmaf(al, y1.x, -y2.x));
      }
#pragma unroll
      for (int i = 0; i < 16; i++) wc[i] = wn[i];
#pragma unroll
      for (int i = 0; i < 4; i++) v[i] = v2[i];
#pragma unroll
      for (int tt = 0; tt < 4; tt++) {
        mma16<false>(d[tt], A[0], A[1], A[2], A[3], G[tt].x, G[tt].y);
        mma16<true>(d[tt], A[4], A[5], A[6], A[7], G[tt].z, G[tt].w);
      }
#pragma unroll
      for (int h = 0; h < 2; h++)
#pragma unroll
        for (int L = 0; L < 2; L++) {
          const uint4 tw = cf[L][2 + h];
          const float2 z0 = cmul(make_float2(d[2 * h][2 * L], d[2 * h][2 * L + 1]), make_float2(__uint_as_float(tw.x), __uint_as_float(tw.y)));
          const float2 z1 = cmul(make_float2(d[2 * h + 1][2 * L], d[2 * h + 1][2 * L + 1]), make_float2(__uint_as_float(tw.z), __uint_as_float(tw.w)));
          A[4 * h + 2 * L] = movm(pack_bf16(z0.x, z1.x)); A[4 * h + 2 * L + 1] = movm(pack_bf16(z0.y, z1.y));
        }
#pragma unroll
      for (int h = 0; h < 2; h++) {
        mma16<false>(d[0], cf[0][1].x, cf[0][1].y, cf[0][1].z, cf[0][1].w, A[4 * h], A[4 * h + 1]);
        mma16<false>(d[1], cf[1][1].x, cf[1][1].y, cf[1][1].z, cf[1][1].w, A[4 * h + 2], A[4 * h + 3]);
#pragma unroll
        for (int e = 0; e < 2; e++)
          sts2(offo + (2 * h + e) * po, set_tag(pack_bf16(d[0][e], d[0][2 + e]), tagv), pack_bf16(d[1][e], d[1][2 + e]));
      }
      CK(12 + ln);
    }
    if (tid == 0) TS(1);
    fence_async_smem();
    if (nl < 2 && wp != 8) bar_arrive(15, NTHR);
    if (wp) bar_arrive(6, NTHR);
    if (!(wp & 7)) {
      bar_sync(wp ? 15 : 6, NTHR);
      if (elect()) tma_st2d(mz2, sz2, cz2, 0);
      if (wp == 0 && elect()) red_add(hz2, 1);
      if (tid == 0) TS(9);
      if (wp == 0) bulk_commit_wait();
      __syncwarp();
    }
  }
  if (wg == 2) {
#pragma unroll 1
    for (int u = 72 + mu, k = 0; u < 216; u += NCTA, k ^= 1) {
      if (R < 0) { fence_async_smem(); bar_sync(4, 128); load_wm(u); }
      mod_unit(sc, u, t128, sbase + O_NRM, full0 + 8 * B_WM, k, red + 256 - 256 * k, tag16);
    }
    fence_async_smem();
    CK(13);
  }

  const int grp = bx / 11, m1 = bx - 11 * grp;
  const bool helper = (m1 & 3) == 3;
  const int f1 = 384 * grp + (helper ? 192 : 128) * (m1 >> 2);
  const int d1 = 160 * (m1 & 3), flip = m1 >= 7;
  const int a1bytes = helper ? 24576 : 16384;
  auto load_a1 = [&](int st, int kb) {
    mbar_expect(full0 + 8 * st, a1bytes);
    tma4d_ef(sbase + st * STAGE, helper ? &maps.w1b : &maps.w1a, 4 * (kb >> 3), 16 * (kb & 7), f1 >> 6, full0 + 8 * st);
  };

  uint32_t bia[4];
  if (wg < 2) {
    const int fa = f1 + (helper ? 128 : 64) * (wg ^ flip) + 16 * (wp & 3) + g, fb = helper ? f1 + 64 + 16 * (wp & 3) + g : fa;
#pragma unroll
    for (int i = 0; i < 4; i++) asm volatile("ld.global.nc.u16 %0, [%1];" : "=r"(bia[i]) : "l"(p.b1 + (i < 2 ? fa : fb) + 8 * (i & 1)) : "memory");
  }
  if (rows) {
#pragma unroll
    for (int kk = 0; kk < 4; kk++) af[kk] = __ldg(p.tab + TB_E + kk * 128 + t128);
    const uint4 c0 = lds4(sbase + O_ST + tid * 16), c1 = lds4(sbase + O_ST + 6144 + tid * 16);
    const uint2 c2 = lds2(sbase + O_ST + 12288 + tid * 8);
    const uint32_t tc[4] = {c0.x, c0.y, c0.z, c0.w}, sy[6] = {c1.x, c1.y, c1.z, c1.w, c2.x, c2.y};
    const uint32_t l8 = pin(8 * l), syl = pin(sbase + O_Y + wp * 2336 + 8 * l);
    uint32_t sh3[3], ham[3];
#pragma unroll
    for (int k = 0; k < 3; k++) {
      const int pos = k && (l >> 4) == k - 1 ? (l & 8) + 4 * (l & 1) + ((l >> 1) & 3) : 4 * (l & 3) + ((l >> 2) & 3);
      const int sw = 2 * cta + ((wp >> 1) & 1), ph = pos ^ ((sw & 3) << 2);
      sh3[k] = pin((l >> 4) * 256 + (wp & 3) * 64 + ph * 4);
      ham[k] = pin(((ph ^ sw) & 7) == 0 ? ~1u : ~0u);
    }
    unsigned* const hh3 = upin(sc->cnt + C_H3 + (cta >> 4));
    uint8_t* const h3g = pin(sc->h3 + (cta >> 4) * (18 * 4096) + (cta & 15) * 256 + (l >> 4) * 3840);
    const int slot = 4 * (cta >> 4) + ((cta >> 1) & 3) + 32 * (2 * ((cta >> 3) & 1) + (cta & 1));
    const uint32_t* zin = sc->z2 + (size_t)slot * 4800;
    if (wg == 2) {
      {
        uint4 v[4];
        const int i3 = min(t128 + 384, 431);
        int it = 0;
        while (true) {
          uint32_t bad = 0;
#pragma unroll
          for (int k = 0; k < 4; k++) v[k] = ld_rlx4(sc->mod + 4 * (k < 3 ? t128 + 128 * k : i3));
#pragma unroll
          for (int k = 0; k < 4; k++) {
            v[k].x ^= tag16; v[k].y ^= tag16; v[k].z ^= tag16; v[k].w ^= tag16;
            bad |= v[k].x | v[k].y | v[k].z | v[k].w;
          }
          if (!any(bad & 0xffffu) || ++it > SPIN_MAX) break;
        }
#pragma unroll
        for (int k = 0; k < 4; k++) sts4(sbase + O_MOD + 16 * (k < 3 ? t128 + 128 * k : i3), v[k].x, v[k].y, v[k].z, v[k].w);
      }
      CK(14);
      bulk_commit_wait();
      bar_sync(10, NTHR);
      mbar_wait(full0 + 8 * B_Z2, 0);
      if (elect()) {
        load_a1(wp - 8, wp - 8);
        if (wp > 8 && wp - 8 < NG1) prefetch_l2(reinterpret_cast<const uint8_t*>(p.w1) + (size_t)(128 * (4 * ((wp - 8) >> 1) + (cta >> 5)) + 64 * (wp & 1) + 2 * (cta & 31)) * (2 * F_), 4 * F_);
      }
      __syncwarp();
    } else {
      const uint4 e0 = lds4(sbase + O_ST + 15360 + tid * 16), e1 = lds4(sbase + O_ST + 19456 + tid * 16), e2 = lds4(sbase + O_ST + 23552 + tid * 16);
      const uint32_t li[9] = {e0.x, e0.y, e0.z, e0.w, e1.x, e1.y, e1.z, e1.w, e2.x}, lx = e2.y, sb3 = e2.z;
      bar_arrive(10, NTHR);
      CK(14);
      if (wp == 1) {
        const uint32_t* zu = upin(zin);
        if (elect()) mbar_expect(full0 + 8 * B_Z2, 19200);
        wait_cnt(sc->cnt + C_Z2, 120 * ep - 40 * STRESS);
        if (elect()) {
          bulk_ld(sbase + O_IN, zu, 19200, full0 + 8 * B_Z2);
          TS(14);
        }
        __syncwarp();
      }
      mbar_wait(full0 + 8 * B_Z2, 0);
      CK(15);
      if (tid == 0) TS(11);
      uint2 v[10];
#pragma unroll
      for (int k1 = 0; k1 < 10; k1++) v[k1] = lds2(k1 < 9 ? li[k1] : lx);
      auto bad3 = [&]() {
        return any(or3(or3(diff2(v[0].x, v[1].x, tag1), diff2(v[2].x, v[3].x, tag1), diff2(v[4].x, v[5].x, tag1)), diff2(v[6].x, v[7].x, tag1), diff2(v[8].x, v[9].x, tag1)) & 1);
      };
      if (__builtin_expect(bad3(), 0)) {
        FAILCNT(1);
        int it = 0;
        do {
#pragma unroll
          for (int k1 = 0; k1 < 10; k1++) v[k1] = ld_rlx2(reinterpret_cast<const uint8_t*>(zin) + ((k1 < 9 ? li[k1] : lx) - (sbase + O_IN)));
        } while (bad3() && ++it < SPIN_MAX);
      }
      float2 za[9], zb[9];
#pragma unroll
      for (int i = 0; i < 9; i++) { za[i] = make_float2(bf_lo(v[i].x), bf_hi(v[i].x)); zb[i] = make_float2(bf_lo(v[i].y), bf_hi(v[i].y)); }
      if ((wp & 3) == wg) {
        const float sp = g ? 0.f : 1.f;
#pragma unroll
        for (int k = 1; k < 5; k++) {
          float2 a = za[k], b = za[9 - k];
          za[k] = make_float2(fmaf(-sp, b.x, a.x), fmaf(sp, b.y, a.y)); za[9 - k] = make_float2(fmaf(sp, a.x, b.x), fmaf(-sp, a.y, b.y));
          a = zb[k]; b = zb[9 - k];
          zb[k] = make_float2(fmaf(-sp, b.x, a.x), fmaf(sp, b.y, a.y)); zb[9 - k] = make_float2(fmaf(sp, a.x, b.x), fmaf(-sp, a.y, b.y));
        }
        za[0].y = g ? za[0].y : bf_lo(v[9].x); zb[0].y = g ? zb[0].y : bf_lo(v[9].y);
      }
      dft9(za); dft9(zb);
#pragma unroll
      for (int n = 0; n < 8; n += 2) {
        const int i0 = (9 - n) % 9, i1 = 8 - n;
        stmatrix4(sb3 + n * 2048, pack_bf16(za[i0].x, zb[i0].x), pack_bf16(za[i0].y, zb[i0].y), pack_bf16(za[i1].x, zb[i1].x), pack_bf16(za[i1].y, zb[i1].y));
      }
      stmatrix2(sb3 + 8 * 2048, pack_bf16(za[1].x, zb[1].x), pack_bf16(za[1].y, zb[1].y));
      fence_async_smem();
    }
    CK(16);
    __syncthreads();
    CK(17);
    float acc[24];
    const uint32_t db = (((sbase + O_B3 + wg * 6144) & 0x3FFFF) >> 4) | ((128 >> 4) << 16);
    wg_fence();
#pragma unroll
    for (int kk = 0; kk < 4; kk++) wgmma_rs_48(acc, af[kk].x, af[kk].y, af[kk].z, af[kk].w, db + kk * 16, 1024 >> 4, kk);
    wg_commit();
    uint32_t ga[9];
    if (wg < 2) {
#pragma unroll
      for (int i = 0; i < 9; i++) { const uint2 v = lds2(l8 + sbase + O_MOD + 256 * i); ga[i] = __byte_perm(v.x, v.y, 0x7632); }
    }
    wg_wait<0>();
    reg_fence(acc);
    CK(18);
#pragma unroll
    for (int i = 0; i < 3; i++) {
      const float* a = &acc[8 * i];
      const uint32_t a0 = pack_bf16(a[0], a[1]), a1 = pack_bf16(a[2], a[3]), a2 = pack_bf16(a[4], a[5]), a3 = pack_bf16(a[6], a[7]);
#pragma unroll
      for (int jh = 0; jh < 2; jh++) {
        float y[4];
        mma16<false>(y, a0, a1, a2, a3, tc[2 * jh], tc[2 * jh + 1]);
        sts(sy[2 * i] + jh * (4 * 584 * 4), pack_bf16(y[0], y[1]));
        sts(sy[2 * i + 1] + jh * (4 * 584 * 4), pack_bf16(y[2], y[3]));
      }
    }
    CK(19);
    if (wg == 2) bar_arrive(7, NTHR); else bar_sync(7, NTHR);
    if (wg) bar_sync(15, NTHR);
    if (wg < 2) {
      CK(20);
      uint2 y[9], sh[9], sw[9];
#pragma unroll
      for (int i = 0; i < 9; i++) y[i] = lds2(syl + 256 * i);
      uint32_t sel = 0x5410, sto = sbase + O_B3 + wg * 9216;
#pragma unroll 1
      for (int e = 0; e < 2; e++, sel = 0x7632, sto += 4608) {
        float a[18];
#pragma unroll
        for (int i = 0; i < 9; i++) {
          const uint32_t x1 = hfma2(ga[i], __byte_perm(y[i].x, y[i].y, sel), xr[i]);
          xr[i] = xr[9 + i]; xr[9 + i] = x1;
          a[2 * i] = bf_lo(x1); a[2 * i + 1] = bf_hi(x1);
        }
#pragma unroll
        for (int i = 0; i < 9; i++) { lds2_if(!e, sh[i], l8 + sbase + O_MOD + 4 * D_ + 256 * i); lds2_if(!e, sw[i], l8 + sbase + O_MOD + 8 * D_ + 256 * i); }
        float oa, ra;
        ln_stats1(a, 1.0f, oa, ra);
#pragma unroll
        for (int i = 0; i < 9; i++) {
          a[2 * i] = fmaf(fmaf(a[2 * i], ra, oa), __uint_as_float(sw[i].x), __uint_as_float(sh[i].x));
          a[2 * i + 1] = fmaf(fmaf(a[2 * i + 1], ra, oa), __uint_as_float(sw[i].y), __uint_as_float(sh[i].y));
        }
        ln_stats1(a, 0.5f, oa, ra);
        uint32_t hv[9];
#pragma unroll
        for (int i = 0; i < 9; i++) hv[i] = bitsel(pack_bf16(fmaf(a[2 * i], ra, oa), fmaf(a[2 * i + 1], ra, oa)), ham[i == 2 ? 1 : i == 6 ? 2 : 0], tag1);
        if (!(wg | e)) {
          if (elect()) red_add(hh3, 1);
#pragma unroll
          for (int i = 0; i < 9; i++) asm volatile("st.global.b32 [%0], %1;" ::"l"(h3g + sh3[i == 2 ? 1 : i == 6 ? 2 : 0] + i * 8192), "r"(hv[i]) : "memory");
          bar_arrive(15, NTHR);
          if (tid == 0) TS(13);
        } else {
#pragma unroll
          for (int i = 0; i < 9; i++) sts(sto + sh3[i == 2 ? 1 : i == 6 ? 2 : 0] + i * 512, hv[i]);
        }
        CK(21 + e);
      }
      fence_async_smem();
      bar_arrive(9, 288);
      CK(23);
    }
  }

  const bool g2 = rows;
  const int z2 = cta, r = z2 >> 6;
  const int s2 = 128 * ((z2 >> 2) & 15), d2 = 144 * (z2 & 3);
  constexpr int ST0 = (32 - JSK - 1) % NST, ST1 = 31 % NST;

  if (wg == 2) {
    asm volatile("setmaxnreg.dec.sync.aligned.u32 40;");
    auto load_b = [&](bool second, int i, int st) {
      const uint32_t lb = full0 + 8 * (B_LAND + st), bytes = second ? 18432 : STAGE - a1bytes;
      mbar_expect(lb, bytes);
      bulk_ld(sbase + (second ? st * STAGE2 + 16384 : st * STAGE + a1bytes),
              second ? sc->u + ((size_t)(36 * r + kb2_order(i)) * D_ + d2) * 128 : sc->h3 + ((size_t)(i * 18 + (d1 >> 5)) << 12), bytes, lb);
    };
    if (wp == 8) {
      int st = rows ? 4 : 0, ph = 1;
#pragma unroll 1
      for (int kb = st; kb < 32; kb++) {
        if (rows && (kb >> 1) == 2) mbar_wait(full0 + 8 * (B_S4 - 4 + kb), 0);
        mbar_wait(empty0 + 8 * st, ph);
        if (elect()) {
          load_a1(st, kb);
          if (kb >= PF2K && kb < PF2K + PF2 && g2)
            prefetch_l2(reinterpret_cast<const uint8_t*>(p.w2) + (size_t)(36 * r + kb2_order(kb - PF2K)) * 262144 + (z2 & 63) * 4096, 4096);
        }
        __syncwarp();
        ring_next<false>(st, ph);
      }
      if (g2) {
        st++;
#pragma unroll 1
        for (int i = 0; i < 36; i++) {
          if (i == HOLDA) mbar_wait(full0 + 8 * B_GO, 0);
          mbar_wait(empty0 + 8 * st, ph);
          if (elect()) {
            mbar_expect(full0 + 8 * st, 16384);
            tma3d_ef(sbase + st * STAGE2, &maps.w2, 64 * (36 * r + kb2_order(i)), s2 >> 6, full0 + 8 * st);
          }
          __syncwarp();
          ring_next<true>(st, ph);
        }
      }
    } else if (wp >= 10) {
      const int sw = wp - 10;
      if (sw) {
        if (rows) {
          bar_sync(9, 288);
          mbar_wait(full0 + 8 * H3W, 0);
          if (elect()) { tma_st3d(&maps.h3, sbase + O_B3 + 4608, 64 * (cta & 15), 18 * (cta >> 4), 1); mbar_arrive(full0 + 8 * B_S4); }
          bulk_commit_wait();
          if (elect()) {
            red_add(sc->cnt + C_H3 + (cta >> 4) + 8, 4);
            mbar_arrive(full0 + 8 * B_S5); mbar_arrive(full0 + 8 * B_S5);
            TS(24);
            asm volatile("fence.acq_rel.gpu;" ::: "memory");
            red_add(&sc->cnt[C_X + 64], 1);
          }
          __syncwarp();
        }
        if (g2) {
          uint2 v[3];
          int it = 0;
          do {
#pragma unroll
            for (int i = 0; i < 3; i++) v[i] = ld_rlx2(sc->mod + 3 * D_ + d2 + 2 * min(l + 32 * i, 71));
          } while (any(or3(diff2(v[0].x, v[0].y, tag16), diff2(v[1].x, v[1].y, tag16), diff2(v[2].x, v[2].y, tag16)) & 0xffffu) && ++it < SPIN_MAX);
#pragma unroll
          for (int i = 0; i < 3; i++) sts(sbase + O_GB + 4 * min(l + 32 * i, 71), __byte_perm(v[i].x, v[i].y, 0x7632));
          __syncwarp();
        }
        wait_cnt<true>(&sc->cnt[C_X + 64], 128 * ep);
        if (elect()) mbar_arrive(full0 + 8 * B_X);
        __syncwarp();
      }
      uint32_t lph = 0;
      auto check_tiles = [&](bool second, int n, int st, uint32_t o1, uint32_t d2nd) {
        const uint32_t b1 = pin(sbase + o1), b2 = pin(sbase + o1 + d2nd);
        int i = 0, it = 0;
#pragma unroll 1
        do {
          const uint32_t so = st * (second ? STAGE2 : STAGE);
          mbar_wait(full0 + 8 * (B_LAND + st), (lph >> st) & 1);
          lph ^= 1u << st;
          uint32_t v[20];
#pragma unroll
          for (int k = 0; k < 20; k++) if (!second || k < 10 || k >= 12) v[k] = lds(k < 12 ? b1 + so + k * 1024 : b2 + so + (k - 12) * 1024); else v[k] = tag1;
#pragma unroll
          for (int k = 0; k < 10; k++) v[k] = diff2(v[2 * k], v[2 * k + 1], tag1);
          const uint32_t bad = or3(or3(or3(v[0], v[1], v[2]), or3(v[3], v[4], v[5]), v[6]), v[7], or3(v[8], v[9], 0));
          if (__builtin_expect(any(bad & 1) && ++it < SPIN_MAX, 0)) {
            FAILCNT(2 + second);
            fence_async_smem();
            __syncwarp();
            if (elect()) load_b(second, i, st);
            __syncwarp();
            continue;
          }
          if (elect()) mbar_arrive(full0 + 8 * st);
          if (++st == NST) st = 0;
          i++;
        } while (i < n);
      };
      if (!sw) check_tiles(false, NV1, 0, a1bytes + l * 32 + (l >> 2) * 4, helper ? 4096 : 12288);
      const bool first = helper || m1 < W0N;
#pragma unroll 1
      for (int k = sw ? first : !first; k <= sw; k++) {
        const uint32_t stg = sbase + (!k ? ST0 * STAGE : helper ? ST1 * STAGE : O_U1);
        const int kbA = (f1 >> 6) + (helper ? 2 : 1) * (k ^ flip), kbB = helper ? (f1 >> 6) + 1 : kbA;
        uint8_t* const uA = upin(sc->u + ((size_t)kbA * D_ + d1) * 128);
        uint8_t* const uB = upin(sc->u + ((size_t)kbB * D_ + (helper ? d1 : d1 + 96)) * 128);
        unsigned* const fA = pin(sc->cnt + C_U + kb2_pos(kbA));
        unsigned* const fB = pin(sc->cnt + C_U + kb2_pos(kbB));
        const bool slow = sw && !helper;
        bar_sync(11 + k, 160);
        if (!slow) { if (elect()) { bulk_st(uA, stg, 96 * 128); TS(k ? 31 : 30); } __syncwarp(); }
        bar_sync(13 + k, 160);
        if (slow) {
          if (g2) mbar_wait(full0 + 8 * B_GO, 0);
          if (first) pause(10 * TRK0);
#pragma unroll 1
          for (int i = 0; i < 20480; i += 2048) {
            if (elect()) bulk_st(uA + i, stg + i, 2048);
            pause(k ? TRKC : TRK0);
          }
        }
        if (elect()) red_add(fA, 1);
        if ((helper ? k : !slow) && elect()) bulk_st(uB, stg + 96 * 128, helper ? 96 * 128 : 64 * 128);
        bulk_commit_wait();
        if (helper && k && elect()) red_add(fB, 1);
        if (elect()) {
          if (!k || helper) mbar_arrive(empty0 + 8 * (k ? ST1 : ST0));
          TS(k ? 23 : 17);
          mbar_arrive(full0 + 8 * B_S5);
        }
        __syncwarp();
      }
      if (sw) {
        mbar_wait(full0 + 8 * B_S5, rows);
        if (elect()) { asm volatile("fence.acq_rel.gpu;" ::: "memory"); red_add(&sc->cnt[C_X], 1); }
        __syncwarp();
      }
      if (g2) {
        if (!sw) check_tiles(true, NV2, 3, 16384 + l * 32 + (4 * (g & 1) + (g >> 1)) * 4, 10240);
        else {
          wait_cnt<true>(&sc->cnt[C_X], NCTA * ep);
          if (elect()) mbar_arrive(full0 + 8 * B_X);
          if (cta == 0) sc->cnt[C_EP + (pin(l) ^ 1)] = ep;
          __syncwarp();
        }
      }
      __syncwarp();
    } else {
      uint32_t ready = 0;
      int st = 0, ph = 1;
#pragma unroll 1
      for (int kb = 0; kb < 32; kb++) {
        const uint8_t* src = upin(sc->h3 + ((size_t)(kb * 18 + (d1 >> 5)) << 12));
        const uint32_t dst = upin(sbase + st * STAGE + a1bytes), lb = full0 + 8 * ((kb < NV1 ? B_LAND : 0) + st);
        if (kb == NV1) { mbar_wait(full0 + 8 * B_X, 0); fence_async_glb(); ready = ~0u; }
        if (rows && (kb >> 1) == 2) mbar_wait(full0 + 8 * (B_S4 - 4 + kb), 0);
        mbar_wait(empty0 + 8 * st, ph);
        if (elect()) mbar_expect(lb, STAGE - a1bytes);
        wait_flags(sc->cnt + C_H3 + l, (kb & 7) + (kb < 8 ? 0 : 8), 64 * ep - 24 * STRESS, ready);
        if (elect()) bulk_ld(dst, src, STAGE - a1bytes, lb);
        ring_next<false>(st, ph);
      }
      if (g2) {
        ready = 0;
        st++;
#pragma unroll 1
        for (int i = 0; i < 36; i++) {
          const int kb = kb2_order(i);
          const uint8_t* src = upin(sc->u + ((size_t)(36 * r + kb) * D_ + d2) * 128);
          const uint32_t dst = upin(sbase + st * STAGE2 + 16384), lb = full0 + 8 * ((i < NV2 ? B_LAND : 0) + st);
          if (i == NV2) { mbar_wait(full0 + 8 * B_X, 1); fence_async_glb(); ready = ~0u; }
          mbar_wait(empty0 + 8 * st, ph);
          if (elect()) mbar_expect(lb, 18432);
          wait_flags(sc->cnt + C_U + 64 * r + l, i & 31, 4 * ep - 2 * STRESS, ready);
          if (elect()) {
            bulk_ld(dst, src, 18432, lb);
            if (i == GOAT) mbar_arrive(full0 + 8 * B_GO);
          }
          ring_next<true>(st, ph);
        }
      }
    }
  } else {
    asm volatile("setmaxnreg.inc.sync.aligned.u32 232;");
    const int wgu = wg;
    constexpr uint32_t sb4 = sbase >> 4;
    const int w = wp & 3;
    Ring rg = {0, 0};
    uint32_t* const x1p = p.out + (size_t)(cta + 128 * ((wp & 3) + 8 * wg)) * 288 + l;
    const uint32_t ad = pin(sbase + (!wg ? ST0 * STAGE : helper ? ST1 * STAGE : O_U1) + (8 * (l >> 4) + (l & 7)) * 128 + (((2 * w + ((l >> 3) & 1)) ^ (l & 7)) << 4));
    const uint32_t uam = pin(g == 2 * t ? 0xfffefffeu : ~0u), uom = tag1 * 0x10001u;
    float acc[96];
    constexpr uint32_t LA = (8192 >> 4) << 16, LB = (4096 >> 4) << 16;
    {
      const float a0 = 0.5f * bf_lo(pin(bia[0])), a1 = 0.5f * bf_lo(pin(bia[1])), b0 = 0.5f * bf_lo(pin(bia[2])), b1 = 0.5f * bf_lo(pin(bia[3]));
#pragma unroll
      for (int i = 0; i < 96; i++) acc[i] = i < 48 ? ((i & 2) ? a1 : a0) : ((i & 2) ? b1 : b0);
      reg_fence(acc);
    }
    if (!helper) gemm_main<0>(acc, sb4 + (wgu ^ flip) * 512 + LA, 0, sb4 + 1024 + LB, wgu, rg, rows, x1p, xr);
    else {
      float ac2[96];
#pragma unroll
      for (int i = 0; i < 96; i++) asm volatile("mov.b32 %0, %1;" : "=f"(ac2[i]) : "f"(acc[i]));
      gemm_main<1>(ac2, sb4 + (wgu ^ flip) * 1024 + LA, sb4 + 512 + LA, sb4 + 1536 + LB, wgu, rg, rows, x1p, xr);
#pragma unroll
      for (int i = 0; i < 96; i++) asm volatile("mov.b32 %0, %1;" : "=f"(acc[i]) : "f"(ac2[i]));
    }
    if (t128 == 0) { TS(wg ? 16 : 6); if (wg) TSC(5); }
    {
      float tp[2] = {0.f, 0.f};
#pragma unroll
      for (int j = 0; j < 12; j++) {
        const float* a = &acc[8 * j];
        const float k3 = j < 2 ? GK3 : fmaf(tp[j & 1], 0.0f, GK3);
        float o[8];
#pragma unroll
        for (int e = 0; e < 8; e++) {
          float z = a[e] * fmaf(a[e] * k3, a[e], GK1);
          asm("tanh.approx.f32 %0, %0;" : "+f"(z));
          if (e == GDEP) tp[j & 1] = z;
          o[e] = fmaf(a[e], z, a[e]);
        }
        stmatrix4t(ad + j * 2048, bitsel(pack_bf16(o[0], o[1]), uam, uom), pack_bf16(o[2], o[3]), bitsel(pack_bf16(o[4], o[5]), uam, uom), pack_bf16(o[6], o[7]));
        if (j == 5) {
          fence_async_smem();
          bar_arrive(11 + wgu, 160);
        }
        if ((j == 5 && helper && !wgu) || (j == 9 && !helper)) break;
      }
      fence_async_smem();
      bar_arrive(13 + wgu, 160);
      if (t128 == 0) TS(wg ? 29 : 28);
    }
    if (g2) {
      const int mb = wgu ^ r;
      const int odd = z2 & 1;
      uint4 gq[4];
      uint2 gs;
      {
        float a0 = 0.f, a1 = 0.f;
        if (wgu) { a0 = __bfloat162float(p.b2[s2 + 64 * mb + 16 * w + g]); a1 = __bfloat162float(p.b2[s2 + 64 * mb + 16 * w + 8 + g]); }
#pragma unroll
        for (int i = 0; i < 4; i++) gq[i] = lds4(sbase + O_GB + 32 * odd + 64 * i + 16 * t);
        gs = lds2(sbase + O_GB + (odd ? 0 : 256) + 8 * t);
#pragma unroll
        for (int i = 0; i < 72; i++) acc[i] = (i & 2) ? a1 : a0;
      }
      uint32_t* const ob = p.out + (size_t)(s2 + 64 * mb + 16 * w + g) * 288 + (d2 >> 1);
      uint32_t* const oq = pin(ob + 8 * odd + 4 * t);
      uint32_t* const os = pin(ob + (odd ? 0 : 64) + 2 * t);
      rg.st++;
      gemm_main<3>(acc, sb4 + mb * 512 + LA, 0, sb4 + 1024 + (1 << 16), wgu, rg, rows, x1p, xr);
      if (t128 == 0) { TS(wg ? 20 : 19); if (wg) TSC(22); }
      auto finish = [&](const float* aq, const float* as) {
#pragma unroll
        for (int i = 0; i < 8; i++) {
          const float* a = aq + 16 * (i >> 1) + 2 * (i & 1);
          const uint4 gv = gq[i >> 1];
          red_bf16x8(oq + (i & 1) * 2304 + 16 * (i >> 1), hmul2(gv.x, pack_bf16(a[0], a[1])), hmul2(gv.y, pack_bf16(a[4], a[5])),
                     hmul2(gv.z, pack_bf16(a[8], a[9])), hmul2(gv.w, pack_bf16(a[12], a[13])));
        }
#pragma unroll
        for (int i = 0; i < 2; i++) red_bf16x4(os + i * 2304, hmul2(gs.x, pack_bf16(as[2 * i], as[2 * i + 1])), hmul2(gs.y, pack_bf16(as[2 * i + 4], as[2 * i + 5])));
      };
      if (odd) finish(&acc[8], &acc[0]); else finish(&acc[0], &acc[64]);
      if (t128 == 0) TS(wg ? 7 : 21);
      __syncwarp();
    }
  }
}

typedef CUresult (*EncodeFn)(CUtensorMap*, CUtensorMapDataType, cuuint32_t, void*, const cuuint64_t*, const cuuint64_t*, const cuuint32_t*,
                             const cuuint32_t*, CUtensorMapInterleave, CUtensorMapSwizzle, CUtensorMapL2promotion, CUtensorMapFloatOOBfill);

struct Dim { cuuint64_t n, stride; cuuint32_t box; };
template <int RANK>
void make_map(EncodeFn enc, CUtensorMap* m, bool words, int swz, const void* ptr, const Dim (&d)[RANK]) {
  cuuint64_t gd[RANK], gs[RANK];
  cuuint32_t bx[RANK], es[RANK];
  for (int i = 0; i < RANK; i++) { gd[i] = d[i].n; gs[i] = d[i].stride; bx[i] = d[i].box; es[i] = 1; }
  enc(m, words ? CU_TENSOR_MAP_DATA_TYPE_UINT32 : CU_TENSOR_MAP_DATA_TYPE_BFLOAT16, RANK, const_cast<void*>(ptr), gd, gs + 1, bx, es,
      CU_TENSOR_MAP_INTERLEAVE_NONE, static_cast<CUtensorMapSwizzle>(swz),
      swz == 3 ? CU_TENSOR_MAP_L2_PROMOTION_L2_256B : CU_TENSOR_MAP_L2_PROMOTION_NONE, CU_TENSOR_MAP_FLOAT_OOB_FILL_NONE);
}

}

extern "C" void kernel_launch(void* const* d_in, const int* in_sizes, int n_in, void* d_out, int out_size) {
  (void)in_sizes; (void)n_in; (void)out_size;
  static EncodeFn enc = nullptr;
  static void *sptr = nullptr, *tptr = nullptr;
  if (!enc) {
    void* f = nullptr; cudaDriverEntryPointQueryResult qr;
    cudaGetDriverEntryPoint("cuTensorMapEncodeTiled", &f, cudaEnableDefault, &qr);
    enc = reinterpret_cast<EncodeFn>(f);
    cudaFuncSetAttribute(fused_kernel, cudaFuncAttributeMaxDynamicSharedMemorySize, SMEM_BYTES);
    cudaGetSymbolAddress(&sptr, g_s);
    cudaGetSymbolAddress(&tptr, T_TAB);
  }
  Params p;
  p.x = (const __nv_bfloat16*)d_in[0]; p.wr = (const __nv_bfloat16*)d_in[1]; p.wi = (const __nv_bfloat16*)d_in[2];
  p.b1 = (const __nv_bfloat16*)d_in[5]; p.b2 = (const __nv_bfloat16*)d_in[7];
  p.c = (const __nv_bfloat16*)d_in[8]; p.wmod = (const __nv_bfloat16*)d_in[9];
  p.w1 = (const __nv_bfloat16*)d_in[4]; p.w2 = (const __nv_bfloat16*)d_in[6];
  p.out = static_cast<uint32_t*>(d_out); p.s = static_cast<Scratch*>(sptr); p.tab = static_cast<const uint4*>(tptr);
  Maps maps;
  make_map<4>(enc, &maps.w1a, false, 3, p.w1, {{64, 0, 64}, {16, 128 * 2 * F_, 4}, {128, 2 * F_, 16}, {72, 128, 2}});
  make_map<4>(enc, &maps.w1b, false, 3, p.w1, {{64, 0, 64}, {16, 128 * 2 * F_, 4}, {128, 2 * F_, 16}, {72, 128, 3}});
  make_map<3>(enc, &maps.w2, false, 3, p.w2, {{64, 0, 64}, {F_, 2 * S_, 64}, {32, 128, 2}});
  make_map<2>(enc, &maps.z1, true, 0, p.s->z1, {{5120, 0, 40}, {120, 20480, 60}});
  for (int i = 0; i < 2; i++) make_map<2>(enc, &maps.z2[i], true, 0, p.s->z2, {{4800, 0, i ? 16u : 24u}, {128, 19200, 128}});
  for (int i = 0; i < 4; i++) make_map<2>(enc, &maps.wf[i], false, 2 - (i & 1), (i & 2) ? p.wi : p.wr, {{16 * DF_, 0, (i & 1) ? 16u : 32u}, {128, 32 * DF_, 128}});
  make_map<2>(enc, &maps.wm, false, 1, p.wmod, {{6 * D_, 0, 16}, {D_, 12 * D_, 192}});
  make_map<3>(enc, &maps.h3, true, 0, p.s->h3, {{1024, 0, 64}, {144, 4096, 18}, {4, 144 * 4096, 3}});
  fused_kernel<<<NCTA, NTHR, SMEM_BYTES, cudaStreamPerThread>>>(p, maps);
}
```

```cpp
#include <cuda_runtime.h>
#include <cuda_bf16.h>
#include <cuda.h>
#include <stdint.h>

namespace {

constexpr int S_ = 2048, D_ = 576, DF_ = 289, F_ = 4608;
constexpr int NCTA = 132, NTHR = 384;
constexpr int STAGE = 36864, NST = 6;
constexpr int STAGE2 = 34816, O_U1 = NST * STAGE2, O_GB = O_U1 + 20480, SMEM_BYTES = 232448;
constexpr uint32_t sbase = 1024, red = sbase + NST * STAGE, full0 = sbase + SMEM_BYTES - 256, empty0 = full0 + 8 * NST;
constexpr int O_NRM = 0, O_B1 = 19456, O_Z1 = 38912, O_P2 = 59392, O_ST = 3 * STAGE;
constexpr int O_RAW = 4 * STAGE;
constexpr int O_IN = 4 * STAGE, O_Y = O_IN + 19456, O_B3 = O_IN + 38912, O_MOD = O_IN + 57344;

__device__ __align__(128) const uint32_t T_TAB[5632] = {
0x3f803f80,0xbf803f80,0x3f803f80,0xbf803f80,0x3f803f80,0xbf803f80,0x3f803f80,0xbf803f80,0x3f803f80,0xbf803f80,0x3f803f80,0xbf803f80,
0x3f803f80,0xbf803f80,0x3f803f80,0xbf803f80,0x3f7f3f80,0xbdc90000,0x3f223f35,0xbf46bf35,0x3f753f7b,0xbe95be48,0x3ef13f0e,0xbf62bf55,
0x3f623f6d,0xbef1bec4,0x3e953ec4,0xbf75bf6d,0x3f463f55,0xbf22bf0e,0x3dc93e48,0xbf7fbf7b,0x3f7b3f80,0xbe480000,0xbe480000,0xbf7bbf80,
0x3f553f6d,0xbf0ebec4,0xbf0ebec4,0xbf55bf6d,0x3f0e3f35,0xbf55bf35,0xbf55bf35,0xbf0ebf35,0x3e483ec4,0xbf7bbf6d,0xbf7bbf6d,0xbe48bec4,
0x3f753f80,0xbe950000,0xbf62bf35,0xbef1bf35,0x3f223f55,0xbf46bf0e,0xbf7fbf7b,0x3dc9be48,0x3dc93ec4,0xbf7fbf6d,0xbf46bf6d,0x3f223ec4,
0xbef1be48,0xbf62bf7b,0xbe95bf0e,0x3f753f55,0x3f6d3f80,0xbec40000,0xbf6dbf80,0x3ec40000,0x3ec43f35,0xbf6dbf35,0xbec4bf35,0x3f6d3f35,
0xbec40000,0xbf6dbf80,0x3ec40000,0x3f6d3f80,0xbf6dbf35,0xbec4bf35,0x3f6d3f35,0x3ec43f35,0x3f623f80,0xbef10000,0xbe95bf35,0x3f753f35,
0x3dc93f0e,0xbf7fbf55,0x3f223e48,0x3f463f7b,0xbf46bec4,0xbf22bf6d,0x3f7f3f6d,0xbdc93ec4,0xbf75bf7b,0x3e95be48,0x3ef13f55,0xbf62bf0e,
0x3f553f80,0xbf0e0000,0x3f0e0000,0x3f553f80,0xbe483ec4,0xbf7bbf6d,0x3f7b3f6d,0xbe483ec4,0xbf7bbf35,0xbe48bf35,0x3e483f35,0xbf7bbf35,
0xbf0ebf6d,0x3f553ec4,0xbf55bec4,0xbf0ebf6d,0x3f463f80,0xbf220000,0x3f7f3f35,0x3dc93f35,0xbef13e48,0xbf62bf7b,0x3e953f55,0xbf75bf0e,
0xbf75bf6d,0x3e95bec4,0xbf62bec4,0xbef1bf6d,0x3dc9bf0e,0x3f7f3f55,0xbf22bf7b,0x3f463e48,0x3f353f80,0xbf350000,0x3f353f80,0xbf350000,
0xbf350000,0xbf35bf80,0xbf350000,0xbf35bf80,0xbf35bf80,0x3f350000,0xbf35bf80,0x3f350000,0x3f350000,0x3f353f80,0x3f350000,0x3f353f80,
0x3f223f80,0xbf460000,0xbdc93f35,0xbf7fbf35,0xbf62be48,0xbef1bf7b,0xbf75bf55,0x3e95bf0e,0xbe95bf6d,0x3f753ec4,0x3ef1bec4,0x3f623f6d,
0x3f7f3f0e,0x3dc93f55,0x3f463f7b,0xbf223e48,0x3f0e3f80,0xbf550000,0xbf550000,0xbf0ebf80,0xbf7bbec4,0xbe48bf6d,0xbe48bf6d,0x3f7b3ec4,
0x3e48bf35,0x3f7b3f35,0x3f7b3f35,0xbe483f35,0x3f553f6d,0xbf0e3ec4,0xbf0e3ec4,0xbf55bf6d,0x3ef13f80,0xbf620000,0xbf75bf35,0x3e95bf35,
0xbf7fbf0e,0x3dc9bf55,0x3f46be48,0x3f223f7b,0x3f22bec4,0x3f463f6d,0x3dc93f6d,0xbf7fbec4,0x3e953f7b,0xbf75be48,0xbf62bf55,0x3ef1bf0e,
0x3ec43f80,0xbf6d0000,0xbec4bf80,0x3f6d0000,0xbf6dbf35,0x3ec4bf35,0x3f6d3f35,0xbec43f35,0x3f6d0000,0x3ec43f80,0xbf6d0000,0xbec4bf80,
0xbec43f35,0xbf6dbf35,0x3ec4bf35,0x3f6d3f35,0x3e953f80,0xbf750000,0x3ef1bf35,0x3f623f35,0xbf46bf55,0x3f22bf0e,0x3dc93f7b,0xbf7fbe48,
0x3f7f3ec4,0xbdc93f6d,0xbf22bf6d,0x3f46bec4,0xbf623e48,0xbef1bf7b,0x3f753f0e,0xbe953f55,0x3e483f80,0xbf7b0000,0x3f7b0000,0x3e483f80,
0xbf0ebf6d,0x3f55bec4,0xbf553ec4,0xbf0ebf6d,0x3f553f35,0xbf0e3f35,0x3f0ebf35,0x3f553f35,0xbf7bbec4,0x3e48bf6d,0xbe483f6d,0xbf7bbec4,
0x3dc93f80,0xbf7f0000,0x3f463f35,0xbf223f35,0xbe95bf7b,0x3f75be48,0xbf62bf0e,0x3ef1bf55,0x3ef13f6d,0xbf623ec4,0x3f753ec4,0xbe953f6d,
0xbf22bf55,0x3f46bf0e,0xbf7fbe48,0x3dc9bf7b,0x3f80,0xbf800000,0x3f80,0xbf800000,0xbf80,0x3f800000,0xbf80,0x3f800000,
0x3f80,0xbf800000,0x3f80,0xbf800000,0xbf80,0x3f800000,0xbf80,0x3f800000,0xbdc93f80,0xbf7f0000,0xbf463f35,0xbf22bf35,
0x3e95bf7b,0x3f753e48,0x3f62bf0e,0x3ef13f55,0xbef13f6d,0xbf62bec4,0xbf753ec4,0xbe95bf6d,0x3f22bf55,0x3f463f0e,0x3f7fbe48,0x3dc93f7b,
0xbe483f80,0xbf7b0000,0xbf7b0000,0x3e48bf80,0x3f0ebf6d,0x3f553ec4,0x3f553ec4,0xbf0e3f6d,0xbf553f35,0xbf0ebf35,0xbf0ebf35,0x3f55bf35,
0x3f7bbec4,0x3e483f6d,0x3e483f6d,0xbf7b3ec4,0xbe953f80,0xbf750000,0xbef1bf35,0x3f62bf35,0x3f46bf55,0x3f223f0e,0xbdc93f7b,0xbf7f3e48,
0xbf7f3ec4,0xbdc9bf6d,0x3f22bf6d,0x3f463ec4,0x3f623e48,0xbef13f7b,0xbf753f0e,0xbe95bf55,0xbec43f80,0xbf6d0000,0x3ec4bf80,0x3f6d0000,
0x3f6dbf35,0x3ec43f35,0xbf6d3f35,0xbec4bf35,0xbf6d0000,0x3ec4bf80,0x3f6d0000,0xbec43f80,0x3ec43f35,0xbf6d3f35,0xbec4bf35,0x3f6dbf35,
0xbef13f80,0xbf620000,0x3f75bf35,0x3e953f35,0x3f7fbf0e,0x3dc93f55,0xbf46be48,0x3f22bf7b,0xbf22bec4,0x3f46bf6d,0xbdc93f6d,0xbf7f3ec4,
0xbe953f7b,0xbf753e48,0x3f62bf55,0x3ef13f0e,0xbf0e3f80,0xbf550000,0x3f550000,0xbf0e3f80,0x3f7bbec4,0xbe483f6d,0x3e48bf6d,0x3f7bbec4,
0xbe48bf35,0x3f7bbf35,0xbf7b3f35,0xbe48bf35,0xbf553f6d,0xbf0ebec4,0x3f0e3ec4,0xbf553f6d,0xbf223f80,0xbf460000,0x3dc93f35,0xbf7f3f35,
0x3f62be48,0xbef13f7b,0x3f75bf55,0x3e953f0e,0x3e95bf6d,0x3f75bec4,0xbef1bec4,0x3f62bf6d,0xbf7f3f0e,0x3dc9bf55,0xbf463f7b,0xbf22be48,
0xbf353f80,0xbf350000,0xbf353f80,0xbf350000,0x3f350000,0xbf353f80,0x3f350000,0xbf353f80,0x3f35bf80,0x3f350000,0x3f35bf80,0x3f350000,
0xbf350000,0x3f35bf80,0xbf350000,0x3f35bf80,0xbf463f80,0xbf220000,0xbf7f3f35,0x3dc9bf35,0x3ef13e48,0xbf623f7b,0xbe953f55,0xbf753f0e,
0x3f75bf6d,0x3e953ec4,0x3f62bec4,0xbef13f6d,0xbdc9bf0e,0x3f7fbf55,0x3f22bf7b,0x3f46be48,0xbf553f80,0xbf0e0000,0xbf0e0000,0x3f55bf80,
0x3e483ec4,0xbf7b3f6d,0xbf7b3f6d,0xbe48bec4,0x3f7bbf35,0xbe483f35,0xbe483f35,0xbf7b3f35,0x3f0ebf6d,0x3f55bec4,0x3f55bec4,0xbf0e3f6d,
0xbf623f80,0xbef10000,0x3e95bf35,0x3f75bf35,0xbdc93f0e,0xbf7f3f55,0xbf223e48,0x3f46bf7b,0x3f46bec4,0xbf223f6d,0xbf7f3f6d,0xbdc9bec4,
0x3f75bf7b,0x3e953e48,0xbef13f55,0xbf623f0e,0xbf6d3f80,0xbec40000,0x3f6dbf80,0x3ec40000,0xbec43f35,0xbf6d3f35,0x3ec4bf35,0x3f6dbf35,
0x3ec40000,0xbf6d3f80,0xbec40000,0x3f6dbf80,0x3f6dbf35,0xbec43f35,0xbf6d3f35,0x3ec4bf35,0xbf753f80,0xbe950000,0x3f62bf35,0xbef13f35,
0xbf223f55,0xbf463f0e,0x3f7fbf7b,0x3dc93e48,0xbdc93ec4,0xbf7f3f6d,0x3f46bf6d,0x3f22bec4,0x3ef1be48,0xbf623f7b,0x3e95bf0e,0x3f75bf55,
0xbf7b3f80,0xbe480000,0x3e480000,0xbf7b3f80,0xbf553f6d,0xbf0e3ec4,0x3f0ebec4,0xbf553f6d,0xbf0e3f35,0xbf553f35,0x3f55bf35,0xbf0e3f35,
0xbe483ec4,0xbf7b3f6d,0x3f7bbf6d,0xbe483ec4,0xbf7f3f80,0xbdc90000,0xbf223f35,0xbf463f35,0xbf753f7b,0xbe953e48,0xbef13f0e,0xbf623f55,
0xbf623f6d,0xbef13ec4,0xbe953ec4,0xbf753f6d,0xbf463f55,0xbf223f0e,0xbdc93e48,0xbf7f3f7b,0x3f803f80,0xbf803f80,0x3f803f80,0xbf803f80,
0x3f803f80,0xbf803f80,0x3f803f80,0xbf803f80,0x3f803f80,0xbf803f80,0x3f803f80,0xbf803f80,0x3f803f80,0xbf803f80,0x3f803f80,0xbf803f80,
0xbdc90000,0xbf7fbf80,0xbf46bf35,0xbf22bf35,0xbe95be48,0xbf75bf7b,0xbf62bf55,0xbef1bf0e,0xbef1bec4,0xbf62bf6d,0xbf75bf6d,0xbe95bec4,
0xbf22bf0e,0xbf46bf55,0xbf7fbf7b,0xbdc9be48,0xbf7bbf80,0x3e480000,0x3e480000,0x3f7b3f80,0xbf55bf6d,0x3f0e3ec4,0x3f0e3ec4,0x3f553f6d,
0xbf0ebf35,0x3f553f35,0x3f553f35,0x3f0e3f35,0xbe48bec4,0x3f7b3f6d,0x3f7b3f6d,0x3e483ec4,0x3e950000,0x3f753f80,0x3ef13f35,0xbf62bf35,
0x3f463f0e,0x3f223f55,0xbdc93e48,0xbf7fbf7b,0x3f7f3f6d,0x3dc93ec4,0xbf22bec4,0xbf46bf6d,0x3f623f7b,0xbef1be48,0xbf75bf55,0xbe95bf0e,
0x3f6d3f80,0xbec40000,0xbf6dbf80,0x3ec40000,0x3ec43f35,0xbf6dbf35,0xbec4bf35,0x3f6d3f35,0xbec40000,0xbf6dbf80,0x3ec40000,0x3f6d3f80,
0xbf6dbf35,0xbec4bf35,0x3f6d3f35,0x3ec43f35,0xbef10000,0xbf62bf80,0x3f753f35,0x3e953f35,0xbf7fbf55,0xbdc9bf0e,0x3f463f7b,0xbf22be48,
0xbf22bf6d,0x3f463ec4,0xbdc93ec4,0xbf7fbf6d,0x3e95be48,0x3f753f7b,0xbf62bf0e,0xbef1bf55,0xbf55bf80,0x3f0e0000,0xbf0e0000,0xbf55bf80,
0x3e48bec4,0x3f7b3f6d,0xbf7bbf6d,0x3e48bec4,0x3f7b3f35,0x3e483f35,0xbe48bf35,0x3f7b3f35,0x3f0e3f6d,0xbf55bec4,0x3f553ec4,0x3f0e3f6d,
0x3f220000,0x3f463f80,0xbdc9bf35,0x3f7f3f35,0x3f623f7b,0xbef13e48,0x3f753f0e,0x3e953f55,0xbe953ec4,0xbf75bf6d,0x3ef13f6d,0xbf62bec4,
0xbf7fbf55,0x3dc9bf0e,0xbf46be48,0xbf22bf7b,0x3f353f80,0xbf350000,0x3f353f80,0xbf350000,0xbf350000,0xbf35bf80,0xbf350000,0xbf35bf80,
0xbf35bf80,0x3f350000,0xbf35bf80,0x3f350000,0x3f350000,0x3f353f80,0x3f350000,0x3f353f80,0xbf460000,0xbf22bf80,0xbf7fbf35,0x3dc9bf35,
0xbef1bf7b,0x3f623e48,0x3e95bf0e,0x3f753f55,0x3f753ec4,0x3e953f6d,0x3f623f6d,0xbef13ec4,0x3dc93f55,0xbf7fbf0e,0xbf223e48,0xbf46bf7b,
0xbf0ebf80,0x3f550000,0x3f550000,0x3f0e3f80,0x3f7b3ec4,0x3e483f6d,0x3e483f6d,0xbf7bbec4,0xbe483f35,0xbf7bbf35,0xbf7bbf35,0x3e48bf35,
0xbf55bf6d,0x3f0ebec4,0x3f0ebec4,0x3f553f6d,0x3f620000,0x3ef13f80,0xbe953f35,0xbf75bf35,0xbdc93f55,0xbf7fbf0e,0xbf22bf7b,0x3f46be48,
0xbf46bf6d,0x3f22bec4,0x3f7f3ec4,0x3dc93f6d,0x3f753e48,0x3e953f7b,0xbef13f0e,0xbf62bf55,0x3ec43f80,0xbf6d0000,0xbec4bf80,0x3f6d0000,
0xbf6dbf35,0x3ec4bf35,0x3f6d3f35,0xbec43f35,0x3f6d0000,0x3ec43f80,0xbf6d0000,0xbec4bf80,0xbec43f35,0xbf6dbf35,0x3ec4bf35,0x3f6d3f35,
0xbf750000,0xbe95bf80,0x3f623f35,0xbef13f35,0x3f22bf0e,0x3f463f55,0xbf7fbe48,0xbdc9bf7b,0xbdc93f6d,0xbf7fbec4,0x3f46bec4,0x3f223f6d,
0xbef1bf7b,0x3f62be48,0xbe953f55,0xbf75bf0e,0xbe48bf80,0x3f7b0000,0xbf7b0000,0xbe48bf80,0x3f0e3f6d,0xbf553ec4,0x3f55bec4,0x3f0e3f6d,
0xbf55bf35,0x3f0ebf35,0xbf0e3f35,0xbf55bf35,0x3f7b3ec4,0xbe483f6d,0x3e48bf6d,0x3f7b3ec4,0x3f7f0000,0x3dc93f80,0x3f22bf35,0x3f463f35,
0xbf753e48,0xbe95bf7b,0xbef13f55,0xbf62bf0e,0x3f62bec4,0x3ef13f6d,0x3e95bf6d,0x3f753ec4,0xbf463f0e,0xbf22bf55,0xbdc93f7b,0xbf7fbe48,
0x3f80,0xbf800000,0x3f80,0xbf800000,0xbf80,0x3f800000,0xbf80,0x3f800000,0x3f80,0xbf800000,0x3f80,0xbf800000,
0xbf80,0x3f800000,0xbf80,0x3f800000,0xbf7f0000,0x3dc9bf80,0xbf22bf35,0x3f46bf35,0x3f753e48,0xbe953f7b,0x3ef13f55,0xbf623f0e,
0xbf62bec4,0x3ef1bf6d,0xbe95bf6d,0x3f75bec4,0x3f463f0e,0xbf223f55,0x3dc93f7b,0xbf7f3e48,0x3e48bf80,0x3f7b0000,0x3f7b0000,0xbe483f80,
0xbf0e3f6d,0xbf55bec4,0xbf55bec4,0x3f0ebf6d,0x3f55bf35,0x3f0e3f35,0x3f0e3f35,0xbf553f35,0xbf7b3ec4,0xbe48bf6d,0xbe48bf6d,0x3f7bbec4,
0x3f750000,0xbe953f80,0xbf623f35,0xbef1bf35,0xbf22bf0e,0x3f46bf55,0x3f7fbe48,0xbdc93f7b,0x3dc93f6d,0xbf7f3ec4,0xbf46bec4,0x3f22bf6d,
0x3ef1bf7b,0x3f623e48,0x3e953f55,0xbf753f0e,0xbec43f80,0xbf6d0000,0x3ec4bf80,0x3f6d0000,0x3f6dbf35,0x3ec43f35,0xbf6d3f35,0xbec4bf35,
0xbf6d0000,0x3ec4bf80,0x3f6d0000,0xbec43f80,0x3ec43f35,0xbf6d3f35,0xbec4bf35,0x3f6dbf35,0xbf620000,0x3ef1bf80,0x3e953f35,0xbf753f35,
0x3dc93f55,0xbf7f3f0e,0x3f22bf7b,0x3f463e48,0x3f46bf6d,0x3f223ec4,0xbf7f3ec4,0x3dc9bf6d,0xbf753e48,0x3e95bf7b,0x3ef13f0e,0xbf623f55,
0x3f0ebf80,0x3f550000,0xbf550000,0x3f0ebf80,0xbf7b3ec4,0x3e48bf6d,0xbe483f6d,0xbf7b3ec4,0x3e483f35,0xbf7b3f35,0x3f7bbf35,0x3e483f35,
0x3f55bf6d,0x3f0e3ec4,0xbf0ebec4,0x3f55bf6d,0x3f460000,0xbf223f80,0x3f7fbf35,0x3dc93f35,0x3ef1bf7b,0x3f62be48,0xbe95bf0e,0x3f75bf55,
0xbf753ec4,0x3e95bf6d,0xbf623f6d,0xbef1bec4,0xbdc93f55,0xbf7f3f0e,0x3f223e48,0xbf463f7b,0xbf353f80,0xbf350000,0xbf353f80,0xbf350000,
0x3f350000,0xbf353f80,0x3f350000,0xbf353f80,0x3f35bf80,0x3f350000,0x3f35bf80,0x3f350000,0xbf350000,0x3f35bf80,0xbf350000,0x3f35bf80,
0xbf220000,0x3f46bf80,0x3dc9bf35,0x3f7fbf35,0xbf623f7b,0xbef1be48,0xbf753f0e,0x3e95bf55,0x3e953ec4,0xbf753f6d,0xbef13f6d,0xbf623ec4,
0x3f7fbf55,0x3dc93f0e,0x3f46be48,0xbf223f7b,0x3f55bf80,0x3f0e0000,0x3f0e0000,0xbf553f80,0xbe48bec4,0x3f7bbf6d,0x3f7bbf6d,0x3e483ec4,
0xbf7b3f35,0x3e48bf35,0x3e48bf35,0x3f7bbf35,0xbf0e3f6d,0xbf553ec4,0xbf553ec4,0x3f0ebf6d,0x3ef10000,0xbf623f80,0xbf753f35,0x3e95bf35,
0x3f7fbf55,0xbdc93f0e,0xbf463f7b,0xbf223e48,0x3f22bf6d,0x3f46bec4,0x3dc93ec4,0xbf7f3f6d,0xbe95be48,0x3f75bf7b,0x3f62bf0e,0xbef13f55,
0xbf6d3f80,0xbec40000,0x3f6dbf80,0x3ec40000,0xbec43f35,0xbf6d3f35,0x3ec4bf35,0x3f6dbf35,0x3ec40000,0xbf6d3f80,0xbec40000,0x3f6dbf80,
0x3f6dbf35,0xbec43f35,0xbf6d3f35,0x3ec4bf35,0xbe950000,0x3f75bf80,0xbef13f35,0xbf623f35,0xbf463f0e,0x3f22bf55,0x3dc93e48,0xbf7f3f7b,
0xbf7f3f6d,0x3dc9bec4,0x3f22bec4,0xbf463f6d,0xbf623f7b,0xbef13e48,0x3f75bf55,0xbe953f0e,0x3f7bbf80,0x3e480000,0xbe480000,0x3f7bbf80,
0x3f55bf6d,0x3f0ebec4,0xbf0e3ec4,0x3f55bf6d,0x3f0ebf35,0x3f55bf35,0xbf553f35,0x3f0ebf35,0x3e48bec4,0x3f7bbf6d,0xbf7b3f6d,0x3e48bec4,
0x3dc90000,0xbf7f3f80,0x3f46bf35,0xbf223f35,0x3e95be48,0xbf753f7b,0x3f62bf55,0xbef13f0e,0x3ef1bec4,0xbf623f6d,0x3f75bf6d,0xbe953ec4,
0x3f22bf0e,0xbf463f55,0x3f7fbf7b,0xbdc93e48,0x3f803f80,0xbf803f80,0x3f803f80,0xbf803f80,0x3f803f80,0xbf803f80,0x3f803f80,0xbf803f80,
0x3f803f80,0xbf803f80,0x3f803f80,0xbf803f80,0x3f803f80,0xbf803f80,0x3f803f80,0xbf803f80,0xbf7fbf80,0x3dc90000,0xbf22bf35,0x3f463f35,
0xbf75bf7b,0x3e953e48,0xbef1bf0e,0x3f623f55,0xbf62bf6d,0x3ef13ec4,0xbe95bec4,0x3f753f6d,0xbf46bf55,0x3f223f0e,0xbdc9be48,0x3f7f3f7b,
0x3f7b3f80,0xbe480000,0xbe480000,0xbf7bbf80,0x3f553f6d,0xbf0ebec4,0xbf0ebec4,0xbf55bf6d,0x3f0e3f35,0xbf55bf35,0xbf55bf35,0xbf0ebf35,
0x3e483ec4,0xbf7bbf6d,0xbf7bbf6d,0xbe48bec4,0xbf75bf80,0x3e950000,0x3f623f35,0x3ef13f35,0xbf22bf55,0x3f463f0e,0x3f7f3f7b,0xbdc93e48,
0xbdc9bec4,0x3f7f3f6d,0x3f463f6d,0xbf22bec4,0x3ef13e48,0x3f623f7b,0x3e953f0e,0xbf75bf55,0x3f6d3f80,0xbec40000,0xbf6dbf80,0x3ec40000,
0x3ec43f35,0xbf6dbf35,0xbec4bf35,0x3f6d3f35,0xbec40000,0xbf6dbf80,0x3ec40000,0x3f6d3f80,0xbf6dbf35,0xbec4bf35,0x3f6d3f35,0x3ec43f35,
0xbf62bf80,0x3ef10000,0x3e953f35,0xbf75bf35,0xbdc9bf0e,0x3f7f3f55,0xbf22be48,0xbf46bf7b,0x3f463ec4,0x3f223f6d,0xbf7fbf6d,0x3dc9bec4,
0x3f753f7b,0xbe953e48,0xbef1bf55,0x3f623f0e,0x3f553f80,0xbf0e0000,0x3f0e0000,0x3f553f80,0xbe483ec4,0xbf7bbf6d,0x3f7b3f6d,0xbe483ec4,
0xbf7bbf35,0xbe48bf35,0x3e483f35,0xbf7bbf35,0xbf0ebf6d,0x3f553ec4,0xbf55bec4,0xbf0ebf6d,0xbf46bf80,0x3f220000,0xbf7fbf35,0xbdc9bf35,
0x3ef1be48,0x3f623f7b,0xbe95bf55,0x3f753f0e,0x3f753f6d,0xbe953ec4,0x3f623ec4,0x3ef13f6d,0xbdc93f0e,0xbf7fbf55,0x3f223f7b,0xbf46be48,
0x3f353f80,0xbf350000,0x3f353f80,0xbf350000,0xbf350000,0xbf35bf80,0xbf350000,0xbf35bf80,0xbf35bf80,0x3f350000,0xbf35bf80,0x3f350000,
0x3f350000,0x3f353f80,0x3f350000,0x3f353f80,0xbf22bf80,0x3f460000,0x3dc9bf35,0x3f7f3f35,0x3f623e48,0x3ef13f7b,0x3f753f55,0xbe953f0e,
0x3e953f6d,0xbf75bec4,0xbef13ec4,0xbf62bf6d,0xbf7fbf0e,0xbdc9bf55,0xbf46bf7b,0x3f22be48,0x3f0e3f80,0xbf550000,0xbf550000,0xbf0ebf80,
0xbf7bbec4,0xbe48bf6d,0xbe48bf6d,0x3f7b3ec4,0x3e48bf35,0x3f7b3f35,0x3f7b3f35,0xbe483f35,0x3f553f6d,0xbf0e3ec4,0xbf0e3ec4,0xbf55bf6d,
0xbef1bf80,0x3f620000,0x3f753f35,0xbe953f35,0x3f7f3f0e,0xbdc93f55,0xbf463e48,0xbf22bf7b,0xbf223ec4,0xbf46bf6d,0xbdc9bf6d,0x3f7f3ec4,
0xbe95bf7b,0x3f753e48,0x3f623f55,0xbef13f0e,0x3ec43f80,0xbf6d0000,0xbec4bf80,0x3f6d0000,0xbf6dbf35,0x3ec4bf35,0x3f6d3f35,0xbec43f35,
0x3f6d0000,0x3ec43f80,0xbf6d0000,0xbec4bf80,0xbec43f35,0xbf6dbf35,0x3ec4bf35,0x3f6d3f35,0xbe95bf80,0x3f750000,0xbef13f35,0xbf62bf35,
0x3f463f55,0xbf223f0e,0xbdc9bf7b,0x3f7f3e48,0xbf7fbec4,0x3dc9bf6d,0x3f223f6d,0xbf463ec4,0x3f62be48,0x3ef13f7b,0xbf75bf0e,0x3e95bf55,
0x3e483f80,0xbf7b0000,0x3f7b0000,0x3e483f80,0xbf0ebf6d,0x3f55bec4,0xbf553ec4,0xbf0ebf6d,0x3f553f35,0xbf0e3f35,0x3f0ebf35,0x3f553f35,
0xbf7bbec4,0x3e48bf6d,0xbe483f6d,0xbf7bbec4,0xbdc9bf80,0x3f7f0000,0xbf46bf35,0x3f22bf35,0x3e953f7b,0xbf753e48,0x3f623f0e,0xbef13f55,
0xbef1bf6d,0x3f62bec4,0xbf75bec4,0x3e95bf6d,0x3f223f55,0xbf463f0e,0x3f7f3e48,0xbdc93f7b,0x3f80,0xbf800000,0x3f80,0xbf800000,
0xbf80,0x3f800000,0xbf80,0x3f800000,0x3f80,0xbf800000,0x3f80,0xbf800000,0xbf80,0x3f800000,0xbf80,0x3f800000,
0x3dc9bf80,0x3f7f0000,0x3f46bf35,0x3f223f35,0xbe953f7b,0xbf75be48,0xbf623f0e,0xbef1bf55,0x3ef1bf6d,0x3f623ec4,0x3f75bec4,0x3e953f6d,
0xbf223f55,0xbf46bf0e,0xbf7f3e48,0xbdc9bf7b,0xbe483f80,0xbf7b0000,0xbf7b0000,0x3e48bf80,0x3f0ebf6d,0x3f553ec4,0x3f553ec4,0xbf0e3f6d,
0xbf553f35,0xbf0ebf35,0xbf0ebf35,0x3f55bf35,0x3f7bbec4,0x3e483f6d,0x3e483f6d,0xbf7b3ec4,0x3e95bf80,0x3f750000,0x3ef13f35,0xbf623f35,
0xbf463f55,0xbf22bf0e,0x3dc9bf7b,0x3f7fbe48,0x3f7fbec4,0x3dc93f6d,0xbf223f6d,0xbf46bec4,0xbf62be48,0x3ef1bf7b,0x3f75bf0e,0x3e953f55,
0xbec43f80,0xbf6d0000,0x3ec4bf80,0x3f6d0000,0x3f6dbf35,0x3ec43f35,0xbf6d3f35,0xbec4bf35,0xbf6d0000,0x3ec4bf80,0x3f6d0000,0xbec43f80,
0x3ec43f35,0xbf6d3f35,0xbec4bf35,0x3f6dbf35,0x3ef1bf80,0x3f620000,0xbf753f35,0xbe95bf35,0xbf7f3f0e,0xbdc9bf55,0x3f463e48,0xbf223f7b,
0x3f223ec4,0xbf463f6d,0x3dc9bf6d,0x3f7fbec4,0x3e95bf7b,0x3f75be48,0xbf623f55,0xbef1bf0e,0xbf0e3f80,0xbf550000,0x3f550000,0xbf0e3f80,
0x3f7bbec4,0xbe483f6d,0x3e48bf6d,0x3f7bbec4,0xbe48bf35,0x3f7bbf35,0xbf7b3f35,0xbe48bf35,0xbf553f6d,0xbf0ebec4,0x3f0e3ec4,0xbf553f6d,
0x3f22bf80,0x3f460000,0xbdc9bf35,0x3f7fbf35,0xbf623e48,0x3ef1bf7b,0xbf753f55,0xbe95bf0e,0xbe953f6d,0xbf753ec4,0x3ef13ec4,0xbf623f6d,
0x3f7fbf0e,0xbdc93f55,0x3f46bf7b,0x3f223e48,0xbf353f80,0xbf350000,0xbf353f80,0xbf350000,0x3f350000,0xbf353f80,0x3f350000,0xbf353f80,
0x3f35bf80,0x3f350000,0x3f35bf80,0x3f350000,0xbf350000,0x3f35bf80,0xbf350000,0x3f35bf80,0x3f46bf80,0x3f220000,0x3f7fbf35,0xbdc93f35,
0xbef1be48,0x3f62bf7b,0x3e95bf55,0x3f75bf0e,0xbf753f6d,0xbe95bec4,0xbf623ec4,0x3ef1bf6d,0x3dc93f0e,0xbf7f3f55,0xbf223f7b,0xbf463e48,
0xbf553f80,0xbf0e0000,0xbf0e0000,0x3f55bf80,0x3e483ec4,0xbf7b3f6d,0xbf7b3f6d,0xbe48bec4,0x3f7bbf35,0xbe483f35,0xbe483f35,0xbf7b3f35,
0x3f0ebf6d,0x3f55bec4,0x3f55bec4,0xbf0e3f6d,0x3f62bf80,0x3ef10000,0xbe953f35,0xbf753f35,0x3dc9bf0e,0x3f7fbf55,0x3f22be48,0xbf463f7b,
0xbf463ec4,0x3f22bf6d,0x3f7fbf6d,0x3dc93ec4,0xbf753f7b,0xbe95be48,0x3ef1bf55,0x3f62bf0e,0xbf6d3f80,0xbec40000,0x3f6dbf80,0x3ec40000,
0xbec43f35,0xbf6d3f35,0x3ec4bf35,0x3f6dbf35,0x3ec40000,0xbf6d3f80,0xbec40000,0x3f6dbf80,0x3f6dbf35,0xbec43f35,0xbf6d3f35,0x3ec4bf35,
0x3f75bf80,0x3e950000,0xbf623f35,0x3ef1bf35,0x3f22bf55,0x3f46bf0e,0xbf7f3f7b,0xbdc9be48,0x3dc9bec4,0x3f7fbf6d,0xbf463f6d,0xbf223ec4,
0xbef13e48,0x3f62bf7b,0xbe953f0e,0xbf753f55,0xbf7b3f80,0xbe480000,0x3e480000,0xbf7b3f80,0xbf553f6d,0xbf0e3ec4,0x3f0ebec4,0xbf553f6d,
0xbf0e3f35,0xbf553f35,0x3f55bf35,0xbf0e3f35,0xbe483ec4,0xbf7b3f6d,0x3f7bbf6d,0xbe483ec4,0x3f7fbf80,0x3dc90000,0x3f22bf35,0x3f46bf35,
0x3f75bf7b,0x3e95be48,0x3ef1bf0e,0x3f62bf55,0x3f62bf6d,0x3ef1bec4,0x3e95bec4,0x3f75bf6d,0x3f46bf55,0x3f22bf0e,0x3dc9be48,0x3f7fbf7b,
0x3f803f80,0xbf803f80,0x3f803f80,0xbf803f80,0x3f803f80,0xbf803f80,0x3f803f80,0xbf803f80,0x3f803f80,0xbf803f80,0x3f803f80,0xbf803f80,
0x3f803f80,0xbf803f80,0x3f803f80,0xbf803f80,0x3dc90000,0x3f7f3f80,0x3f463f35,0x3f223f35,0x3e953e48,0x3f753f7b,0x3f623f55,0x3ef13f0e,
0x3ef13ec4,0x3f623f6d,0x3f753f6d,0x3e953ec4,0x3f223f0e,0x3f463f55,0x3f7f3f7b,0x3dc93e48,0xbf7bbf80,0x3e480000,0x3e480000,0x3f7b3f80,
0xbf55bf6d,0x3f0e3ec4,0x3f0e3ec4,0x3f553f6d,0xbf0ebf35,0x3f553f35,0x3f553f35,0x3f0e3f35,0xbe48bec4,0x3f7b3f6d,0x3f7b3f6d,0x3e483ec4,
0xbe950000,0xbf75bf80,0xbef1bf35,0x3f623f35,0xbf46bf0e,0xbf22bf55,0x3dc9be48,0x3f7f3f7b,0xbf7fbf6d,0xbdc9bec4,0x3f223ec4,0x3f463f6d,
0xbf62bf7b,0x3ef13e48,0x3f753f55,0x3e953f0e,0x3f6d3f80,0xbec40000,0xbf6dbf80,0x3ec40000,0x3ec43f35,0xbf6dbf35,0xbec4bf35,0x3f6d3f35,
0xbec40000,0xbf6dbf80,0x3ec40000,0x3f6d3f80,0xbf6dbf35,0xbec4bf35,0x3f6d3f35,0x3ec43f35,0x3ef10000,0x3f623f80,0xbf75bf35,0xbe95bf35,
0x3f7f3f55,0x3dc93f0e,0xbf46bf7b,0x3f223e48,0x3f223f6d,0xbf46bec4,0x3dc9bec4,0x3f7f3f6d,0xbe953e48,0xbf75bf7b,0x3f623f0e,0x3ef13f55,
0xbf55bf80,0x3f0e0000,0xbf0e0000,0xbf55bf80,0x3e48bec4,0x3f7b3f6d,0xbf7bbf6d,0x3e48bec4,0x3f7b3f35,0x3e483f35,0xbe48bf35,0x3f7b3f35,
0x3f0e3f6d,0xbf55bec4,0x3f553ec4,0x3f0e3f6d,0xbf220000,0xbf46bf80,0x3dc93f35,0xbf7fbf35,0xbf62bf7b,0x3ef1be48,0xbf75bf0e,0xbe95bf55,
0x3e95bec4,0x3f753f6d,0xbef1bf6d,0x3f623ec4,0x3f7f3f55,0xbdc93f0e,0x3f463e48,0x3f223f7b,0x3f353f80,0xbf350000,0x3f353f80,0xbf350000,
0xbf350000,0xbf35bf80,0xbf350000,0xbf35bf80,0xbf35bf80,0x3f350000,0xbf35bf80,0x3f350000,0x3f350000,0x3f353f80,0x3f350000,0x3f353f80,
0x3f460000,0x3f223f80,0x3f7f3f35,0xbdc93f35,0x3ef13f7b,0xbf62be48,0xbe953f0e,0xbf75bf55,0xbf75bec4,0xbe95bf6d,0xbf62bf6d,0x3ef1bec4,
0xbdc9bf55,0x3f7f3f0e,0x3f22be48,0x3f463f7b,0xbf0ebf80,0x3f550000,0x3f550000,0x3f0e3f80,0x3f7b3ec4,0x3e483f6d,0x3e483f6d,0xbf7bbec4,
0xbe483f35,0xbf7bbf35,0xbf7bbf35,0x3e48bf35,0xbf55bf6d,0x3f0ebec4,0x3f0ebec4,0x3f553f6d,0xbf620000,0xbef1bf80,0x3e95bf35,0x3f753f35,
0x3dc9bf55,0x3f7f3f0e,0x3f223f7b,0xbf463e48,0x3f463f6d,0xbf223ec4,0xbf7fbec4,0xbdc9bf6d,0xbf75be48,0xbe95bf7b,0x3ef1bf0e,0x3f623f55,
0x3ec43f80,0xbf6d0000,0xbec4bf80,0x3f6d0000,0xbf6dbf35,0x3ec4bf35,0x3f6d3f35,0xbec43f35,0x3f6d0000,0x3ec43f80,0xbf6d0000,0xbec4bf80,
0xbec43f35,0xbf6dbf35,0x3ec4bf35,0x3f6d3f35,0x3f750000,0x3e953f80,0xbf62bf35,0x3ef1bf35,0xbf223f0e,0xbf46bf55,0x3f7f3e48,0x3dc93f7b,
0x3dc9bf6d,0x3f7f3ec4,0xbf463ec4,0xbf22bf6d,0x3ef13f7b,0xbf623e48,0x3e95bf55,0x3f753f0e,0xbe48bf80,0x3f7b0000,0xbf7b0000,0xbe48bf80,
0x3f0e3f6d,0xbf553ec4,0x3f55bec4,0x3f0e3f6d,0xbf55bf35,0x3f0ebf35,0xbf0e3f35,0xbf55bf35,0x3f7b3ec4,0xbe483f6d,0x3e48bf6d,0x3f7b3ec4,
0xbf7f0000,0xbdc9bf80,0xbf223f35,0xbf46bf35,0x3f75be48,0x3e953f7b,0x3ef1bf55,0x3f623f0e,0xbf623ec4,0xbef1bf6d,0xbe953f6d,0xbf75bec4,
0x3f46bf0e,0x3f223f55,0x3dc9bf7b,0x3f7f3e48,0x3f80,0xbf800000,0x3f80,0xbf800000,0xbf80,0x3f800000,0xbf80,0x3f800000,
0x3f80,0xbf800000,0x3f80,0xbf800000,0xbf80,0x3f800000,0xbf80,0x3f800000,0x3f7f0000,0xbdc93f80,0x3f223f35,0xbf463f35,
0xbf75be48,0x3e95bf7b,0xbef1bf55,0x3f62bf0e,0x3f623ec4,0xbef13f6d,0x3e953f6d,0xbf753ec4,0xbf46bf0e,0x3f22bf55,0xbdc9bf7b,0x3f7fbe48,
0x3e48bf80,0x3f7b0000,0x3f7b0000,0xbe483f80,0xbf0e3f6d,0xbf55bec4,0xbf55bec4,0x3f0ebf6d,0x3f55bf35,0x3f0e3f35,0x3f0e3f35,0xbf553f35,
0xbf7b3ec4,0xbe48bf6d,0xbe48bf6d,0x3f7bbec4,0xbf750000,0x3e95bf80,0x3f62bf35,0x3ef13f35,0x3f223f0e,0xbf463f55,0xbf7f3e48,0x3dc9bf7b,
0xbdc9bf6d,0x3f7fbec4,0x3f463ec4,0xbf223f6d,0xbef13f7b,0xbf62be48,0xbe95bf55,0x3f75bf0e,0xbec43f80,0xbf6d0000,0x3ec4bf80,0x3f6d0000,
0x3f6dbf35,0x3ec43f35,0xbf6d3f35,0xbec4bf35,0xbf6d0000,0x3ec4bf80,0x3f6d0000,0xbec43f80,0x3ec43f35,0xbf6d3f35,0xbec4bf35,0x3f6dbf35,
0x3f620000,0xbef13f80,0xbe95bf35,0x3f75bf35,0xbdc9bf55,0x3f7fbf0e,0xbf223f7b,0xbf46be48,0xbf463f6d,0xbf22bec4,0x3f7fbec4,0xbdc93f6d,
0x3f75be48,0xbe953f7b,0xbef1bf0e,0x3f62bf55,0x3f0ebf80,0x3f550000,0xbf550000,0x3f0ebf80,0xbf7b3ec4,0x3e48bf6d,0xbe483f6d,0xbf7b3ec4,
0x3e483f35,0xbf7b3f35,0x3f7bbf35,0x3e483f35,0x3f55bf6d,0x3f0e3ec4,0xbf0ebec4,0x3f55bf6d,0xbf460000,0x3f22bf80,0xbf7f3f35,0xbdc9bf35,
0xbef13f7b,0xbf623e48,0x3e953f0e,0xbf753f55,0x3f75bec4,0xbe953f6d,0x3f62bf6d,0x3ef13ec4,0x3dc9bf55,0x3f7fbf0e,0xbf22be48,0x3f46bf7b,
0xbf353f80,0xbf350000,0xbf353f80,0xbf350000,0x3f350000,0xbf353f80,0x3f350000,0xbf353f80,0x3f35bf80,0x3f350000,0x3f35bf80,0x3f350000,
0xbf350000,0x3f35bf80,0xbf350000,0x3f35bf80,0x3f220000,0xbf463f80,0xbdc93f35,0xbf7f3f35,0x3f62bf7b,0x3ef13e48,0x3f75bf0e,0xbe953f55,
0xbe95bec4,0x3f75bf6d,0x3ef1bf6d,0x3f62bec4,0xbf7f3f55,0xbdc9bf0e,0xbf463e48,0x3f22bf7b,0x3f55bf80,0x3f0e0000,0x3f0e0000,0xbf553f80,
0xbe48bec4,0x3f7bbf6d,0x3f7bbf6d,0x3e483ec4,0xbf7b3f35,0x3e48bf35,0x3e48bf35,0x3f7bbf35,0xbf0e3f6d,0xbf553ec4,0xbf553ec4,0x3f0ebf6d,
0xbef10000,0x3f62bf80,0x3f75bf35,0xbe953f35,0xbf7f3f55,0x3dc9bf0e,0x3f46bf7b,0x3f22be48,0xbf223f6d,0xbf463ec4,0xbdc9bec4,0x3f7fbf6d,
0x3e953e48,0xbf753f7b,0xbf623f0e,0x3ef1bf55,0xbf6d3f80,0xbec40000,0x3f6dbf80,0x3ec40000,0xbec43f35,0xbf6d3f35,0x3ec4bf35,0x3f6dbf35,
0x3ec40000,0xbf6d3f80,0xbec40000,0x3f6dbf80,0x3f6dbf35,0xbec43f35,0xbf6d3f35,0x3ec4bf35,0x3e950000,0xbf753f80,0x3ef1bf35,0x3f62bf35,
0x3f46bf0e,0xbf223f55,0xbdc9be48,0x3f7fbf7b,0x3f7fbf6d,0xbdc93ec4,0xbf223ec4,0x3f46bf6d,0x3f62bf7b,0x3ef1be48,0xbf753f55,0x3e95bf0e,
0x3f7bbf80,0x3e480000,0xbe480000,0x3f7bbf80,0x3f55bf6d,0x3f0ebec4,0xbf0e3ec4,0x3f55bf6d,0x3f0ebf35,0x3f55bf35,0xbf553f35,0x3f0ebf35,
0x3e48bec4,0x3f7bbf6d,0xbf7b3f6d,0x3e48bec4,0xbdc90000,0x3f7fbf80,0xbf463f35,0x3f22bf35,0xbe953e48,0x3f75bf7b,0xbf623f55,0x3ef1bf0e,
0xbef13ec4,0x3f62bf6d,0xbf753f6d,0x3e95bec4,0xbf223f0e,0x3f46bf55,0xbf7f3f7b,0x3dc9be48,0x40003f80,0x3fb53f80,0x3f80,0xbfb53f80,
0x40004000,0xbfb50000,0x0,0xbfb5c000,0x40004000,0xbfb5c000,0x0,0x3fb50000,0x40004000,0x3fb50000,0x0,0x3fb54000,
0x3fff3f80,0x3fa23f80,0xbe49bf80,0xbfc6bf80,0x3ff53ffb,0xbfe2bec8,0xbf15bec8,0xbf71bffb,0x3fe23fed,0xbf15bfed,0xbf71bf44,0x3ff53f44,
0x3fc63fd5,0x3fff3f8e,0xbfa2bf8e,0x3e493fd5,0x3ffb3f80,0x3f8e3f80,0xbec83f80,0xbfd53f80,0x3fd53fed,0xbffbbf44,0xbf8ebf44,0xbec8bfed,
0x3f8e3fb5,0x3ec8bfb5,0xbfd5bfb5,0x3ffb3fb5,0x3ec83f44,0x3fd53fed,0xbffbbfed,0xbf8e3f44,0x3ff53f80,0x3f713f80,0xbf15bf80,0xbfe2bf80,
0x3fa23fd5,0xbfffbf8e,0xbfc6bf8e,0x3e49bfd5,0x3e493f44,0x3fa2bf44,0xbfffbfed,0x3fc63fed,0xbf71bec8,0x3f153ffb,0xbfe2bffb,0xbff5bec8,
0x3fed3f80,0x3f443f80,0xbf443f80,0xbfed3f80,0x3f443fb5,0xbfedbfb5,0xbfedbfb5,0x3f44bfb5,0xbf440000,0x3fed0000,0xbfedc000,0x3f444000,
0xbfedbfb5,0xbf443fb5,0xbf44bfb5,0xbfedbfb5,0x3fe23f80,0x3f153f80,0xbf71bf80,0xbff5bf80,0x3e493f8e,0xbfc6bfd5,0xbfffbfd5,0x3fa2bf8e,
0xbfc6bf44,0x3fff3f44,0xbfa2bfed,0xbe493fed,0xbff5bffb,0xbfe23ec8,0x3f15bec8,0xbf71bffb,0x3fd53f80,0x3ec83f80,0xbf8e3f80,0xbffb3f80,
0xbec83f44,0xbf8ebfed,0xbffbbfed,0x3fd5bf44,0xbffbbfb5,0x3fd53fb5,0xbec8bfb5,0xbf8e3fb5,0xbf8ebfed,0xbffbbf44,0x3fd53f44,0x3ec8bfed,
0x3fc63f80,0x3e493f80,0xbfa2bf80,0xbfffbf80,0xbf713ec8,0xbf15bffb,0xbfe2bffb,0x3ff5bec8,0xbff5bfed,0x3f713fed,0x3f15bf44,0xbfe23f44,
0x3e49bf8e,0xbfa2bfd5,0x3fff3fd5,0x3fc6bf8e,0x3f80,0xbfb53f80,0xc0003f80,0xbfb53f80,0xc000,0x3fb50000,0x40000000,0xbfb54000,
0x4000,0x3fb5c000,0xc0000000,0x3fb50000,0xc000,0xbfb50000,0x40000000,0x3fb5c000,0xbe493f80,0xbfc63f80,0xbfffbf80,0xbfa2bf80,
0x3f15bffb,0x3f713ec8,0x3ff53ec8,0xbfe23ffb,0xbf713fed,0x3ff5bfed,0xbfe2bf44,0x3f153f44,0x3fa2bfd5,0xbe49bf8e,0x3fc63f8e,0x3fffbfd5,
0xbec83f80,0xbfd53f80,0xbffb3f80,0xbf8e3f80,0x3f8ebfed,0x3ec83f44,0x3fd53f44,0xbffb3fed,0xbfd53fb5,0x3ffbbfb5,0xbf8ebfb5,0xbec83fb5,
0x3ffbbf44,0x3f8ebfed,0x3ec83fed,0x3fd5bf44,0xbf153f80,0xbfe23f80,0xbff5bf80,0xbf71bf80,0x3fc6bfd5,0xbe493f8e,0x3fa23f8e,0xbfff3fd5,
0xbfff3f44,0x3fc6bf44,0xbe49bfed,0xbfa23fed,0x3fe23ec8,0x3ff5bffb,0xbf713ffb,0x3f153ec8,0xbf443f80,0xbfed3f80,0xbfed3f80,0xbf443f80,
0x3fedbfb5,0xbf443fb5,0x3f443fb5,0xbfed3fb5,0xbfed0000,0x3f440000,0x3f44c000,0xbfed4000,0x3f443fb5,0x3fedbfb5,0xbfed3fb5,0xbf443fb5,
0xbf713f80,0xbff53f80,0xbfe2bf80,0xbf15bf80,0x3fffbf8e,0xbfa23fd5,0x3e493fd5,0xbfc63f8e,0xbfa2bf44,0xbe493f44,0x3fc6bfed,0xbfff3fed,
0xbf153ffb,0x3f71bec8,0xbff53ec8,0xbfe23ffb,0xbf8e3f80,0xbffb3f80,0xbfd53f80,0xbec83f80,0x3ffbbf44,0xbfd53fed,0xbec83fed,0xbf8e3f44,
0xbec8bfb5,0xbf8e3fb5,0x3ffbbfb5,0xbfd53fb5,0xbfd53fed,0xbec83f44,0xbf8ebf44,0xbffb3fed,0xbfa23f80,0xbfff3f80,0xbfc6bf80,0xbe49bf80,
0x3fe2bec8,0xbff53ffb,0xbf713ffb,0xbf153ec8,0x3f15bfed,0xbfe23fed,0x3ff5bf44,0xbf713f44,0xbfff3f8e,0xbfc63fd5,0x3e49bfd5,0xbfa23f8e,
0xc0003f80,0xbfb53f80,0x3f80,0x3fb53f80,0xc0004000,0x3fb50000,0x0,0x3fb5c000,0xc0004000,0x3fb5c000,0x0,0xbfb50000,
0xc0004000,0xbfb50000,0x0,0xbfb54000,0xbfff3f80,0xbfa23f80,0x3e49bf80,0x3fc6bf80,0xbff53ffb,0x3fe2bec8,0x3f15bec8,0x3f71bffb,
0xbfe23fed,0x3f15bfed,0x3f71bf44,0xbff53f44,0xbfc63fd5,0xbfff3f8e,0x3fa2bf8e,0xbe493fd5,0xbffb3f80,0xbf8e3f80,0x3ec83f80,0x3fd53f80,
0xbfd53fed,0x3ffbbf44,0x3f8ebf44,0x3ec8bfed,0xbf8e3fb5,0xbec8bfb5,0x3fd5bfb5,0xbffb3fb5,0xbec83f44,0xbfd53fed,0x3ffbbfed,0x3f8e3f44,
0xbff53f80,0xbf713f80,0x3f15bf80,0x3fe2bf80,0xbfa23fd5,0x3fffbf8e,0x3fc6bf8e,0xbe49bfd5,0xbe493f44,0xbfa2bf44,0x3fffbfed,0xbfc63fed,
0x3f71bec8,0xbf153ffb,0x3fe2bffb,0x3ff5bec8,0xbfed3f80,0xbf443f80,0x3f443f80,0x3fed3f80,0xbf443fb5,0x3fedbfb5,0x3fedbfb5,0xbf44bfb5,
0x3f440000,0xbfed0000,0x3fedc000,0xbf444000,0x3fedbfb5,0x3f443fb5,0x3f44bfb5,0x3fedbfb5,0xbfe23f80,0xbf153f80,0x3f71bf80,0x3ff5bf80,
0xbe493f8e,0x3fc6bfd5,0x3fffbfd5,0xbfa2bf8e,0x3fc6bf44,0xbfff3f44,0x3fa2bfed,0x3e493fed,0x3ff5bffb,0x3fe23ec8,0xbf15bec8,0x3f71bffb,
0xbfd53f80,0xbec83f80,0x3f8e3f80,0x3ffb3f80,0x3ec83f44,0x3f8ebfed,0x3ffbbfed,0xbfd5bf44,0x3ffbbfb5,0xbfd53fb5,0x3ec8bfb5,0x3f8e3fb5,
0x3f8ebfed,0x3ffbbf44,0xbfd53f44,0xbec8bfed,0xbfc63f80,0xbe493f80,0x3fa2bf80,0x3fffbf80,0x3f713ec8,0x3f15bffb,0x3fe2bffb,0xbff5bec8,
0x3ff5bfed,0xbf713fed,0xbf15bf44,0x3fe23f44,0xbe49bf8e,0x3fa2bfd5,0xbfff3fd5,0xbfc6bf8e,0x3f80,0x3fb53f80,0x40003f80,0x3fb53f80,
0xc000,0xbfb50000,0xc0000000,0x3fb54000,0x4000,0xbfb5c000,0x40000000,0xbfb50000,0xc000,0x3fb50000,0xc0000000,0xbfb5c000,
0x3e493f80,0x3fc63f80,0x3fffbf80,0x3fa2bf80,0xbf15bffb,0xbf713ec8,0xbff53ec8,0x3fe23ffb,0x3f713fed,0xbff5bfed,0x3fe2bf44,0xbf153f44,
0xbfa2bfd5,0x3e49bf8e,0xbfc63f8e,0xbfffbfd5,0x3ec83f80,0x3fd53f80,0x3ffb3f80,0x3f8e3f80,0xbf8ebfed,0xbec83f44,0xbfd53f44,0x3ffb3fed,
0x3fd53fb5,0xbffbbfb5,0x3f8ebfb5,0x3ec83fb5,0xbffbbf44,0xbf8ebfed,0xbec83fed,0xbfd5bf44,0x3f153f80,0x3fe23f80,0x3ff5bf80,0x3f71bf80,
0xbfc6bfd5,0x3e493f8e,0xbfa23f8e,0x3fff3fd5,0x3fff3f44,0xbfc6bf44,0x3e49bfed,0x3fa23fed,0xbfe23ec8,0xbff5bffb,0x3f713ffb,0xbf153ec8,
0x3f443f80,0x3fed3f80,0x3fed3f80,0x3f443f80,0xbfedbfb5,0x3f443fb5,0xbf443fb5,0x3fed3fb5,0x3fed0000,0xbf440000,0xbf44c000,0x3fed4000,
0xbf443fb5,0xbfedbfb5,0x3fed3fb5,0x3f443fb5,0x3f713f80,0x3ff53f80,0x3fe2bf80,0x3f15bf80,0xbfffbf8e,0x3fa23fd5,0xbe493fd5,0x3fc63f8e,
0x3fa2bf44,0x3e493f44,0xbfc6bfed,0x3fff3fed,0x3f153ffb,0xbf71bec8,0x3ff53ec8,0x3fe23ffb,0x3f8e3f80,0x3ffb3f80,0x3fd53f80,0x3ec83f80,
0xbffbbf44,0x3fd53fed,0x3ec83fed,0x3f8e3f44,0x3ec8bfb5,0x3f8e3fb5,0xbffbbfb5,0x3fd53fb5,0x3fd53fed,0x3ec83f44,0x3f8ebf44,0x3ffb3fed,
0x3fa23f80,0x3fff3f80,0x3fc6bf80,0x3e49bf80,0xbfe2bec8,0x3ff53ffb,0x3f713ffb,0x3f153ec8,0xbf15bfed,0x3fe23fed,0xbff5bf44,0x3f713f44,
0x3fff3f8e,0x3fc63fd5,0xbe49bfd5,0x3fa23f8e,0x40004000,0x3fb54000,0x0,0xbfb50000,0x40004000,0xbfb50000,0x0,0xbfb5c000,
0x40004000,0xbfb5c000,0x0,0x3fb50000,0x40004000,0x3fb50000,0x0,0x3fb54000,0x3fa23fb5,0xbe493fb5,0xbfc6bfb5,0xbfffbfb5,
0x3f713f8e,0xbff5bfd5,0xbfe2bfd5,0x3f15bf8e,0x3f153f44,0x3f71bf44,0xbff5bfed,0x3fe23fed,0x3e493ec8,0x3fc63ffb,0xbfffbffb,0xbfa23ec8,
0xbec80000,0xbfd50000,0xbffbc000,0xbf8ec000,0xbf8ebf44,0xbec8bfed,0xbfd5bfed,0x3ffb3f44,0xbfd5bfb5,0x3ffb3fb5,0xbf8ebfb5,0xbec83fb5,
0xbffbbfed,0xbf8e3f44,0xbec8bf44,0xbfd5bfed,0xbfe2bfb5,0xbff5bfb5,0xbf71bfb5,0x3f15bfb5,0xbfffbffb,0x3fc6bec8,0x3e49bec8,0x3fa23ffb,
0xbfc6bfed,0x3e493fed,0x3fa23f44,0xbfffbf44,0xbf15bf8e,0xbfe2bfd5,0x3ff53fd5,0x3f71bf8e,0xbfedc000,0xbf44c000,0x3f440000,0x3fed0000,
0xbf44bfb5,0x3fed3fb5,0x3fed3fb5,0xbf443fb5,0x3f440000,0xbfed0000,0x3fed4000,0xbf44c000,0x3fed3fb5,0x3f44bfb5,0x3f443fb5,0x3fed3fb5,
0xbf15bfb5,0x3f71bfb5,0x3ff53fb5,0x3fe23fb5,0x3fa23ec8,0x3e493ffb,0x3fc63ffb,0xbfffbec8,0x3fff3fed,0xbfa2bfed,0xbe493f44,0x3fc6bf44,
0x3f713fd5,0x3ff53f8e,0xbfe2bf8e,0xbf153fd5,0x3f8e0000,0x3ffb0000,0x3fd54000,0x3ec84000,0x3ffb3fed,0xbfd53f44,0xbec83f44,0xbf8ebfed,
0x3ec83fb5,0x3f8ebfb5,0xbffbbfb5,0x3fd53fb5,0xbfd5bf44,0xbec83fed,0xbf8ebfed,0xbffbbf44,0x3fff3fb5,0x3fc63fb5,0x3e493fb5,0xbfa23fb5,
0x3f153fd5,0xbfe2bf8e,0xbff5bf8e,0x3f71bfd5,0xbfe2bf44,0x3ff53f44,0xbf71bfed,0xbf153fed,0xbfa2bffb,0xbfffbec8,0x3fc63ec8,0x3e49bffb,
0x4000,0xbfb54000,0xc0000000,0xbfb50000,0xc000,0x3fb50000,0x40000000,0xbfb54000,0x4000,0x3fb5c000,0xc0000000,0x3fb50000,
0xc000,0xbfb50000,0x40000000,0x3fb5c000,0xbfc63fb5,0xbfff3fb5,0xbfa2bfb5,0x3e49bfb5,0x3fe2bf8e,0xbf153fd5,0x3f713fd5,0xbff53f8e,
0xbff53f44,0x3fe2bf44,0xbf15bfed,0xbf713fed,0x3fffbec8,0x3fa2bffb,0x3e493ffb,0x3fc6bec8,0xbffb0000,0xbf8e0000,0x3ec8c000,0x3fd5c000,
0x3fd53f44,0xbffb3fed,0xbf8e3fed,0xbec8bf44,0xbf8ebfb5,0xbec83fb5,0x3fd5bfb5,0xbffb3fb5,0x3ec83fed,0x3fd5bf44,0xbffb3f44,0xbf8e3fed,
0xbf71bfb5,0x3f15bfb5,0x3fe2bfb5,0x3ff5bfb5,0xbe493ffb,0xbfa23ec8,0xbfff3ec8,0x3fc6bffb,0x3fa2bfed,0xbfff3fed,0x3fc63f44,0xbe49bf44,
0xbff53f8e,0xbf713fd5,0xbf15bfd5,0xbfe23f8e,0x3f44c000,0x3fedc000,0x3fed0000,0x3f440000,0xbfed3fb5,0x3f44bfb5,0xbf44bfb5,0x3fedbfb5,
0x3fed0000,0xbf440000,0xbf444000,0x3fedc000,0xbf44bfb5,0xbfed3fb5,0x3fedbfb5,0x3f44bfb5,0x3ff5bfb5,0x3fe2bfb5,0x3f153fb5,0xbf713fb5,
0xbfc6bec8,0x3fffbffb,0x3fa2bffb,0x3e493ec8,0xbe493fed,0x3fc6bfed,0xbfff3f44,0x3fa2bf44,0x3fe2bfd5,0x3f15bf8e,0x3f713f8e,0x3ff5bfd5,
0x3fd50000,0x3ec80000,0xbf8e4000,0xbffb4000,0x3ec8bfed,0x3f8ebf44,0x3ffbbf44,0xbfd53fed,0xbffb3fb5,0x3fd5bfb5,0xbec8bfb5,0xbf8e3fb5,
0x3f8e3f44,0x3ffbbfed,0xbfd53fed,0xbec83f44,0x3e493fb5,0xbfa23fb5,0xbfff3fb5,0xbfc63fb5,0x3ff5bfd5,0xbf713f8e,0x3f153f8e,0xbfe23fd5,
0xbf71bf44,0xbf153f44,0x3fe2bfed,0xbff53fed,0xbfc63ffb,0xbe493ec8,0xbfa2bec8,0xbfff3ffb,0xc0004000,0xbfb54000,0x0,0x3fb50000,
0xc0004000,0x3fb50000,0x0,0x3fb5c000,0xc0004000,0x3fb5c000,0x0,0xbfb50000,0xc0004000,0xbfb50000,0x0,0xbfb54000,
0xbfa23fb5,0x3e493fb5,0x3fc6bfb5,0x3fffbfb5,0xbf713f8e,0x3ff5bfd5,0x3fe2bfd5,0xbf15bf8e,0xbf153f44,0xbf71bf44,0x3ff5bfed,0xbfe23fed,
0xbe493ec8,0xbfc63ffb,0x3fffbffb,0x3fa23ec8,0x3ec80000,0x3fd50000,0x3ffbc000,0x3f8ec000,0x3f8ebf44,0x3ec8bfed,0x3fd5bfed,0xbffb3f44,
0x3fd5bfb5,0xbffb3fb5,0x3f8ebfb5,0x3ec83fb5,0x3ffbbfed,0x3f8e3f44,0x3ec8bf44,0x3fd5bfed,0x3fe2bfb5,0x3ff5bfb5,0x3f71bfb5,0xbf15bfb5,
0x3fffbffb,0xbfc6bec8,0xbe49bec8,0xbfa23ffb,0x3fc6bfed,0xbe493fed,0xbfa23f44,0x3fffbf44,0x3f15bf8e,0x3fe2bfd5,0xbff53fd5,0xbf71bf8e,
0x3fedc000,0x3f44c000,0xbf440000,0xbfed0000,0x3f44bfb5,0xbfed3fb5,0xbfed3fb5,0x3f443fb5,0xbf440000,0x3fed0000,0xbfed4000,0x3f44c000,
0xbfed3fb5,0xbf44bfb5,0xbf443fb5,0xbfed3fb5,0x3f15bfb5,0xbf71bfb5,0xbff53fb5,0xbfe23fb5,0xbfa23ec8,0xbe493ffb,0xbfc63ffb,0x3fffbec8,
0xbfff3fed,0x3fa2bfed,0x3e493f44,0xbfc6bf44,0xbf713fd5,0xbff53f8e,0x3fe2bf8e,0x3f153fd5,0xbf8e0000,0xbffb0000,0xbfd54000,0xbec84000,
0xbffb3fed,0x3fd53f44,0x3ec83f44,0x3f8ebfed,0xbec83fb5,0xbf8ebfb5,0x3ffbbfb5,0xbfd53fb5,0x3fd5bf44,0x3ec83fed,0x3f8ebfed,0x3ffbbf44,
0xbfff3fb5,0xbfc63fb5,0xbe493fb5,0x3fa23fb5,0xbf153fd5,0x3fe2bf8e,0x3ff5bf8e,0xbf71bfd5,0x3fe2bf44,0xbff53f44,0x3f71bfed,0x3f153fed,
0x3fa2bffb,0x3fffbec8,0xbfc63ec8,0xbe49bffb,0x4000,0x3fb54000,0x40000000,0x3fb50000,0xc000,0xbfb50000,0xc0000000,0x3fb54000,
0x4000,0xbfb5c000,0x40000000,0xbfb50000,0xc000,0x3fb50000,0xc0000000,0xbfb5c000,0x3fc63fb5,0x3fff3fb5,0x3fa2bfb5,0xbe49bfb5,
0xbfe2bf8e,0x3f153fd5,0xbf713fd5,0x3ff53f8e,0x3ff53f44,0xbfe2bf44,0x3f15bfed,0x3f713fed,0xbfffbec8,0xbfa2bffb,0xbe493ffb,0xbfc6bec8,
0x3ffb0000,0x3f8e0000,0xbec8c000,0xbfd5c000,0xbfd53f44,0x3ffb3fed,0x3f8e3fed,0x3ec8bf44,0x3f8ebfb5,0x3ec83fb5,0xbfd5bfb5,0x3ffb3fb5,
0xbec83fed,0xbfd5bf44,0x3ffb3f44,0x3f8e3fed,0x3f71bfb5,0xbf15bfb5,0xbfe2bfb5,0xbff5bfb5,0x3e493ffb,0x3fa23ec8,0x3fff3ec8,0xbfc6bffb,
0xbfa2bfed,0x3fff3fed,0xbfc63f44,0x3e49bf44,0x3ff53f8e,0x3f713fd5,0x3f15bfd5,0x3fe23f8e,0xbf44c000,0xbfedc000,0xbfed0000,0xbf440000,
0x3fed3fb5,0xbf44bfb5,0x3f44bfb5,0xbfedbfb5,0xbfed0000,0x3f440000,0x3f444000,0xbfedc000,0x3f44bfb5,0x3fed3fb5,0xbfedbfb5,0xbf44bfb5,
0xbff5bfb5,0xbfe2bfb5,0xbf153fb5,0x3f713fb5,0x3fc6bec8,0xbfffbffb,0xbfa2bffb,0xbe493ec8,0x3e493fed,0xbfc6bfed,0x3fff3f44,0xbfa2bf44,
0xbfe2bfd5,0xbf15bf8e,0xbf713f8e,0xbff5bfd5,0xbfd50000,0xbec80000,0x3f8e4000,0x3ffb4000,0xbec8bfed,0xbf8ebf44,0xbffbbf44,0x3fd53fed,
0x3ffb3fb5,0xbfd5bfb5,0x3ec8bfb5,0x3f8e3fb5,0xbf8e3f44,0xbffbbfed,0x3fd53fed,0x3ec83f44,0xbe493fb5,0x3fa23fb5,0x3fff3fb5,0x3fc63fb5,
0xbff5bfd5,0x3f713f8e,0xbf153f8e,0x3fe23fd5,0x3f71bf44,0x3f153f44,0xbfe2bfed,0x3ff53fed,0x3fc63ffb,0x3e493ec8,0x3fa2bec8,0x3fff3ffb,
0x40004000,0x3fb54000,0x0,0xbfb50000,0x40004000,0xbfb50000,0x0,0xbfb5c000,0x40004000,0xbfb5c000,0x0,0x3fb50000,
0x40004000,0x3fb50000,0x0,0x3fb54000,0xbe490000,0xbfc60000,0xbfffc000,0xbfa2c000,0xbf15bec8,0xbf71bffb,0xbff5bffb,0x3fe23ec8,
0xbf71bf44,0x3ff53f44,0xbfe2bfed,0x3f153fed,0xbfa2bf8e,0x3e493fd5,0xbfc6bfd5,0xbfffbf8e,0xbffbc000,0xbf8ec000,0x3ec80000,0x3fd50000,
0xbfd5bfed,0x3ffb3f44,0x3f8e3f44,0x3ec83fed,0xbf8ebfb5,0xbec83fb5,0x3fd53fb5,0xbffbbfb5,0xbec8bf44,0xbfd5bfed,0x3ffb3fed,0x3f8ebf44,
0x3f150000,0x3fe20000,0x3ff54000,0x3f714000,0x3fc63f8e,0xbe493fd5,0x3fa23fd5,0xbfffbf8e,0x3fff3fed,0xbfc6bfed,0x3e493f44,0x3fa2bf44,
0x3fe23ffb,0x3ff53ec8,0xbf71bec8,0x3f153ffb,0x3fed4000,0x3f444000,0xbf440000,0xbfed0000,0x3f443fb5,0xbfedbfb5,0xbfedbfb5,0x3f44bfb5,
0xbf440000,0x3fed0000,0xbfedc000,0x3f444000,0xbfedbfb5,0xbf443fb5,0xbf44bfb5,0xbfedbfb5,0xbf710000,0xbff50000,0xbfe2c000,0xbf15c000,
0xbfffbfd5,0x3fa2bf8e,0xbe49bf8e,0x3fc63fd5,0xbfa2bfed,0xbe493fed,0x3fc63f44,0xbfffbf44,0x3f15bec8,0xbf71bffb,0x3ff53ffb,0x3fe2bec8,
0xbfd5c000,0xbec8c000,0x3f8e0000,0x3ffb0000,0x3ec8bf44,0x3f8e3fed,0x3ffb3fed,0xbfd53f44,0x3ffb3fb5,0xbfd5bfb5,0x3ec83fb5,0x3f8ebfb5,
0x3f8e3fed,0x3ffb3f44,0xbfd5bf44,0xbec83fed,0x3fa20000,0x3fff0000,0x3fc64000,0x3e494000,0x3fe23ffb,0xbff53ec8,0xbf713ec8,0xbf15bffb,
0xbf153f44,0x3fe2bf44,0xbff5bfed,0x3f713fed,0xbfffbfd5,0xbfc63f8e,0x3e49bf8e,0xbfa2bfd5,0x4000,0xbfb54000,0xc0000000,0xbfb50000,
0xc000,0x3fb50000,0x40000000,0xbfb54000,0x4000,0x3fb5c000,0xc0000000,0x3fb50000,0xc000,0xbfb50000,0x40000000,0x3fb5c000,
0xbfff0000,0xbfa20000,0x3e49c000,0x3fc6c000,0x3ff53ec8,0xbfe23ffb,0xbf153ffb,0xbf71bec8,0xbfe2bf44,0x3f153f44,0x3f71bfed,0xbff53fed,
0x3fc63f8e,0x3fffbfd5,0xbfa23fd5,0x3e493f8e,0x3ec8c000,0x3fd5c000,0x3ffb0000,0x3f8e0000,0xbf8e3fed,0xbec8bf44,0xbfd5bf44,0x3ffbbfed,
0x3fd5bfb5,0xbffb3fb5,0x3f8e3fb5,0x3ec8bfb5,0xbffb3f44,0xbf8e3fed,0xbec8bfed,0xbfd53f44,0x3ff50000,0x3f710000,0xbf154000,0xbfe24000,
0xbfa2bf8e,0x3fffbfd5,0x3fc6bfd5,0xbe493f8e,0x3e493fed,0x3fa2bfed,0xbfff3f44,0x3fc6bf44,0x3f71bffb,0xbf15bec8,0x3fe23ec8,0x3ff5bffb,
0xbf444000,0xbfed4000,0xbfed0000,0xbf440000,0x3fedbfb5,0xbf443fb5,0x3f443fb5,0xbfed3fb5,0xbfed0000,0x3f440000,0x3f44c000,0xbfed4000,
0x3f443fb5,0x3fedbfb5,0xbfed3fb5,0xbf443fb5,0xbfe20000,0xbf150000,0x3f71c000,0x3ff5c000,0x3e493fd5,0xbfc63f8e,0xbfff3f8e,0x3fa2bfd5,
0x3fc6bfed,0xbfff3fed,0x3fa23f44,0x3e49bf44,0xbff53ec8,0xbfe23ffb,0x3f15bffb,0xbf713ec8,0x3f8ec000,0x3ffbc000,0x3fd50000,0x3ec80000,
0xbffb3f44,0x3fd5bfed,0x3ec8bfed,0x3f8ebf44,0x3ec83fb5,0x3f8ebfb5,0xbffb3fb5,0x3fd5bfb5,0x3fd5bfed,0x3ec8bf44,0x3f8e3f44,0x3ffbbfed,
0x3fc60000,0x3e490000,0xbfa24000,0xbfff4000,0x3f71bffb,0x3f15bec8,0x3fe2bec8,0xbff53ffb,0xbff53f44,0x3f71bf44,0x3f15bfed,0xbfe23fed,
0xbe493fd5,0x3fa2bf8e,0xbfff3f8e,0xbfc63fd5,0xc0004000,0xbfb54000,0x0,0x3fb50000,0xc0004000,0x3fb50000,0x0,0x3fb5c000,
0xc0004000,0x3fb5c000,0x0,0xbfb50000,0xc0004000,0xbfb50000,0x0,0xbfb54000,0x3e490000,0x3fc60000,0x3fffc000,0x3fa2c000,
0x3f15bec8,0x3f71bffb,0x3ff5bffb,0xbfe23ec8,0x3f71bf44,0xbff53f44,0x3fe2bfed,0xbf153fed,0x3fa2bf8e,0xbe493fd5,0x3fc6bfd5,0x3fffbf8e,
0x3ffbc000,0x3f8ec000,0xbec80000,0xbfd50000,0x3fd5bfed,0xbffb3f44,0xbf8e3f44,0xbec83fed,0x3f8ebfb5,0x3ec83fb5,0xbfd53fb5,0x3ffbbfb5,
0x3ec8bf44,0x3fd5bfed,0xbffb3fed,0xbf8ebf44,0xbf150000,0xbfe20000,0xbff54000,0xbf714000,0xbfc63f8e,0x3e493fd5,0xbfa23fd5,0x3fffbf8e,
0xbfff3fed,0x3fc6bfed,0xbe493f44,0xbfa2bf44,0xbfe23ffb,0xbff53ec8,0x3f71bec8,0xbf153ffb,0xbfed4000,0xbf444000,0x3f440000,0x3fed0000,
0xbf443fb5,0x3fedbfb5,0x3fedbfb5,0xbf44bfb5,0x3f440000,0xbfed0000,0x3fedc000,0xbf444000,0x3fedbfb5,0x3f443fb5,0x3f44bfb5,0x3fedbfb5,
0x3f710000,0x3ff50000,0x3fe2c000,0x3f15c000,0x3fffbfd5,0xbfa2bf8e,0x3e49bf8e,0xbfc63fd5,0x3fa2bfed,0x3e493fed,0xbfc63f44,0x3fffbf44,
0xbf15bec8,0x3f71bffb,0xbff53ffb,0xbfe2bec8,0x3fd5c000,0x3ec8c000,0xbf8e0000,0xbffb0000,0xbec8bf44,0xbf8e3fed,0xbffb3fed,0x3fd53f44,
0xbffb3fb5,0x3fd5bfb5,0xbec83fb5,0xbf8ebfb5,0xbf8e3fed,0xbffb3f44,0x3fd5bf44,0x3ec83fed,0xbfa20000,0xbfff0000,0xbfc64000,0xbe494000,
0xbfe23ffb,0x3ff53ec8,0x3f713ec8,0x3f15bffb,0x3f153f44,0xbfe2bf44,0x3ff5bfed,0xbf713fed,0x3fffbfd5,0x3fc63f8e,0xbe49bf8e,0x3fa2bfd5,
0x4000,0x3fb54000,0x40000000,0x3fb50000,0xc000,0xbfb50000,0xc0000000,0x3fb54000,0x4000,0xbfb5c000,0x40000000,0xbfb50000,
0xc000,0x3fb50000,0xc0000000,0xbfb5c000,0x3fff0000,0x3fa20000,0xbe49c000,0xbfc6c000,0xbff53ec8,0x3fe23ffb,0x3f153ffb,0x3f71bec8,
0x3fe2bf44,0xbf153f44,0xbf71bfed,0x3ff53fed,0xbfc63f8e,0xbfffbfd5,0x3fa23fd5,0xbe493f8e,0xbec8c000,0xbfd5c000,0xbffb0000,0xbf8e0000,
0x3f8e3fed,0x3ec8bf44,0x3fd5bf44,0xbffbbfed,0xbfd5bfb5,0x3ffb3fb5,0xbf8e3fb5,0xbec8bfb5,0x3ffb3f44,0x3f8e3fed,0x3ec8bfed,0x3fd53f44,
0xbff50000,0xbf710000,0x3f154000,0x3fe24000,0x3fa2bf8e,0xbfffbfd5,0xbfc6bfd5,0x3e493f8e,0xbe493fed,0xbfa2bfed,0x3fff3f44,0xbfc6bf44,
0xbf71bffb,0x3f15bec8,0xbfe23ec8,0xbff5bffb,0x3f444000,0x3fed4000,0x3fed0000,0x3f440000,0xbfedbfb5,0x3f443fb5,0xbf443fb5,0x3fed3fb5,
0x3fed0000,0xbf440000,0xbf44c000,0x3fed4000,0xbf443fb5,0xbfedbfb5,0x3fed3fb5,0x3f443fb5,0x3fe20000,0x3f150000,0xbf71c000,0xbff5c000,
0xbe493fd5,0x3fc63f8e,0x3fff3f8e,0xbfa2bfd5,0xbfc6bfed,0x3fff3fed,0xbfa23f44,0xbe49bf44,0x3ff53ec8,0x3fe23ffb,0xbf15bffb,0x3f713ec8,
0xbf8ec000,0xbffbc000,0xbfd50000,0xbec80000,0x3ffb3f44,0xbfd5bfed,0xbec8bfed,0xbf8ebf44,0xbec83fb5,0xbf8ebfb5,0x3ffb3fb5,0xbfd5bfb5,
0xbfd5bfed,0xbec8bf44,0xbf8e3f44,0xbffbbfed,0xbfc60000,0xbe490000,0x3fa24000,0x3fff4000,0xbf71bffb,0xbf15bec8,0xbfe2bec8,0x3ff53ffb,
0x3ff53f44,0xbf71bf44,0xbf15bfed,0x3fe23fed,0x3e493fd5,0xbfa2bf8e,0x3fff3f8e,0x3fc63fd5,0x40004000,0x3fb54000,0x0,0xbfb50000,
0x40004000,0xbfb50000,0x0,0xbfb5c000,0x40004000,0xbfb5c000,0x0,0x3fb50000,0x40004000,0x3fb50000,0x0,0x3fb54000,
0xbfc6bfb5,0xbfffbfb5,0xbfa2bfb5,0x3e49bfb5,0xbfe2bfd5,0x3f15bf8e,0xbf71bf8e,0x3ff53fd5,0xbff5bfed,0x3fe23fed,0xbf15bf44,0xbf713f44,
0xbfffbffb,0xbfa23ec8,0xbe49bec8,0xbfc6bffb,0x3ec80000,0x3fd50000,0x3ffb4000,0x3f8e4000,0x3f8e3f44,0x3ec83fed,0x3fd53fed,0xbffbbf44,
0x3fd53fb5,0xbffbbfb5,0x3f8e3fb5,0x3ec8bfb5,0x3ffb3fed,0x3f8ebf44,0x3ec83f44,0x3fd53fed,0x3f713fb5,0xbf153fb5,0xbfe2bfb5,0xbff5bfb5,
0xbe493ec8,0xbfa2bffb,0xbfffbffb,0x3fc6bec8,0xbfa2bf44,0x3fff3f44,0xbfc6bfed,0x3e493fed,0xbff5bfd5,0xbf713f8e,0xbf15bf8e,0xbfe2bfd5,
0xbfedc000,0xbf44c000,0x3f440000,0x3fed0000,0xbf44bfb5,0x3fed3fb5,0x3fed3fb5,0xbf443fb5,0x3f440000,0xbfed0000,0x3fed4000,0xbf44c000,
0x3fed3fb5,0x3f44bfb5,0x3f443fb5,0x3fed3fb5,0x3ff53fb5,0x3fe23fb5,0x3f153fb5,0xbf713fb5,0x3fc63ffb,0xbfffbec8,0xbfa2bec8,0xbe49bffb,
0xbe493f44,0x3fc6bf44,0xbfffbfed,0x3fa23fed,0xbfe2bf8e,0xbf153fd5,0xbf71bfd5,0xbff5bf8e,0xbf8e0000,0xbffb0000,0xbfd5c000,0xbec8c000,
0xbffbbfed,0x3fd5bf44,0x3ec8bf44,0x3f8e3fed,0xbec8bfb5,0xbf8e3fb5,0x3ffb3fb5,0xbfd5bfb5,0x3fd53f44,0x3ec8bfed,0x3f8e3fed,0x3ffb3f44,
0xbe49bfb5,0x3fa2bfb5,0x3fff3fb5,0x3fc63fb5,0x3ff53f8e,0xbf713fd5,0x3f153fd5,0xbfe2bf8e,0x3f713fed,0x3f15bfed,0xbfe2bf44,0x3ff53f44,
0xbfc6bec8,0xbe493ffb,0xbfa2bffb,0xbfffbec8,0x4000,0xbfb54000,0xc0000000,0xbfb50000,0xc000,0x3fb50000,0x40000000,0xbfb54000,
0x4000,0x3fb5c000,0xc0000000,0x3fb50000,0xc000,0xbfb50000,0x40000000,0x3fb5c000,0xbfa2bfb5,0x3e49bfb5,0x3fc6bfb5,0x3fffbfb5,
0x3f713fd5,0xbff53f8e,0xbfe23f8e,0x3f15bfd5,0xbf15bfed,0xbf713fed,0x3ff5bf44,0xbfe23f44,0x3e493ffb,0x3fc6bec8,0xbfff3ec8,0xbfa23ffb,
0x3ffb0000,0x3f8e0000,0xbec84000,0xbfd54000,0xbfd5bf44,0x3ffbbfed,0x3f8ebfed,0x3ec83f44,0x3f8e3fb5,0x3ec8bfb5,0xbfd53fb5,0x3ffbbfb5,
0xbec8bfed,0xbfd53f44,0x3ffbbf44,0x3f8ebfed,0xbfe23fb5,0xbff53fb5,0xbf71bfb5,0x3f15bfb5,0x3fffbec8,0xbfc63ffb,0xbe493ffb,0xbfa23ec8,
0xbfc6bf44,0x3e493f44,0x3fa2bfed,0xbfff3fed,0x3f153fd5,0x3fe2bf8e,0xbff53f8e,0xbf713fd5,0x3f44c000,0x3fedc000,0x3fed0000,0x3f440000,
0xbfed3fb5,0x3f44bfb5,0xbf44bfb5,0x3fedbfb5,0x3fed0000,0xbf440000,0xbf444000,0x3fedc000,0xbf44bfb5,0xbfed3fb5,0x3fedbfb5,0x3f44bfb5,
0x3f153fb5,0xbf713fb5,0xbff53fb5,0xbfe23fb5,0x3fa2bffb,0x3e493ec8,0x3fc63ec8,0xbfff3ffb,0xbfff3f44,0x3fa2bf44,0x3e49bfed,0xbfc63fed,
0x3f713f8e,0x3ff5bfd5,0xbfe23fd5,0xbf153f8e,0xbfd50000,0xbec80000,0x3f8ec000,0x3ffbc000,0xbec83fed,0xbf8e3f44,0xbffb3f44,0x3fd5bfed,
0x3ffbbfb5,0xbfd53fb5,0x3ec83fb5,0x3f8ebfb5,0xbf8ebf44,0xbffb3fed,0x3fd5bfed,0x3ec8bf44,0x3fffbfb5,0x3fc6bfb5,0x3e493fb5,0xbfa23fb5,
0xbf15bf8e,0x3fe2bfd5,0x3ff5bfd5,0xbf713f8e,0xbfe23fed,0x3ff5bfed,0xbf71bf44,0xbf153f44,0x3fa23ec8,0x3fffbffb,0xbfc63ffb,0xbe493ec8,
0xc0004000,0xbfb54000,0x0,0x3fb50000,0xc0004000,0x3fb50000,0x0,0x3fb5c000,0xc0004000,0x3fb5c000,0x0,0xbfb50000,
0xc0004000,0xbfb50000,0x0,0xbfb54000,0x3fc6bfb5,0x3fffbfb5,0x3fa2bfb5,0xbe49bfb5,0x3fe2bfd5,0xbf15bf8e,0x3f71bf8e,0xbff53fd5,
0x3ff5bfed,0xbfe23fed,0x3f15bf44,0x3f713f44,0x3fffbffb,0x3fa23ec8,0x3e49bec8,0x3fc6bffb,0xbec80000,0xbfd50000,0xbffb4000,0xbf8e4000,
0xbf8e3f44,0xbec83fed,0xbfd53fed,0x3ffbbf44,0xbfd53fb5,0x3ffbbfb5,0xbf8e3fb5,0xbec8bfb5,0xbffb3fed,0xbf8ebf44,0xbec83f44,0xbfd53fed,
0xbf713fb5,0x3f153fb5,0x3fe2bfb5,0x3ff5bfb5,0x3e493ec8,0x3fa2bffb,0x3fffbffb,0xbfc6bec8,0x3fa2bf44,0xbfff3f44,0x3fc6bfed,0xbe493fed,
0x3ff5bfd5,0x3f713f8e,0x3f15bf8e,0x3fe2bfd5,0x3fedc000,0x3f44c000,0xbf440000,0xbfed0000,0x3f44bfb5,0xbfed3fb5,0xbfed3fb5,0x3f443fb5,
0xbf440000,0x3fed0000,0xbfed4000,0x3f44c000,0xbfed3fb5,0xbf44bfb5,0xbf443fb5,0xbfed3fb5,0xbff53fb5,0xbfe23fb5,0xbf153fb5,0x3f713fb5,
0xbfc63ffb,0x3fffbec8,0x3fa2bec8,0x3e49bffb,0x3e493f44,0xbfc6bf44,0x3fffbfed,0xbfa23fed,0x3fe2bf8e,0x3f153fd5,0x3f71bfd5,0x3ff5bf8e,
0x3f8e0000,0x3ffb0000,0x3fd5c000,0x3ec8c000,0x3ffbbfed,0xbfd5bf44,0xbec8bf44,0xbf8e3fed,0x3ec8bfb5,0x3f8e3fb5,0xbffb3fb5,0x3fd5bfb5,
0xbfd53f44,0xbec8bfed,0xbf8e3fed,0xbffb3f44,0x3e49bfb5,0xbfa2bfb5,0xbfff3fb5,0xbfc63fb5,0xbff53f8e,0x3f713fd5,0xbf153fd5,0x3fe2bf8e,
0xbf713fed,0xbf15bfed,0x3fe2bf44,0xbff53f44,0x3fc6bec8,0x3e493ffb,0x3fa2bffb,0x3fffbec8,0x4000,0x3fb54000,0x40000000,0x3fb50000,
0xc000,0xbfb50000,0xc0000000,0x3fb54000,0x4000,0xbfb5c000,0x40000000,0xbfb50000,0xc000,0x3fb50000,0xc0000000,0xbfb5c000,
0x3fa2bfb5,0xbe49bfb5,0xbfc6bfb5,0xbfffbfb5,0xbf713fd5,0x3ff53f8e,0x3fe23f8e,0xbf15bfd5,0x3f15bfed,0x3f713fed,0xbff5bf44,0x3fe23f44,
0xbe493ffb,0xbfc6bec8,0x3fff3ec8,0x3fa23ffb,0xbffb0000,0xbf8e0000,0x3ec84000,0x3fd54000,0x3fd5bf44,0xbffbbfed,0xbf8ebfed,0xbec83f44,
0xbf8e3fb5,0xbec8bfb5,0x3fd53fb5,0xbffbbfb5,0x3ec8bfed,0x3fd53f44,0xbffbbf44,0xbf8ebfed,0x3fe23fb5,0x3ff53fb5,0x3f71bfb5,0xbf15bfb5,
0xbfffbec8,0x3fc63ffb,0x3e493ffb,0x3fa23ec8,0x3fc6bf44,0xbe493f44,0xbfa2bfed,0x3fff3fed,0xbf153fd5,0xbfe2bf8e,0x3ff53f8e,0x3f713fd5,
0xbf44c000,0xbfedc000,0xbfed0000,0xbf440000,0x3fed3fb5,0xbf44bfb5,0x3f44bfb5,0xbfedbfb5,0xbfed0000,0x3f440000,0x3f444000,0xbfedc000,
0x3f44bfb5,0x3fed3fb5,0xbfedbfb5,0xbf44bfb5,0xbf153fb5,0x3f713fb5,0x3ff53fb5,0x3fe23fb5,0xbfa2bffb,0xbe493ec8,0xbfc63ec8,0x3fff3ffb,
0x3fff3f44,0xbfa2bf44,0xbe49bfed,0x3fc63fed,0xbf713f8e,0xbff5bfd5,0x3fe23fd5,0x3f153f8e,0x3fd50000,0x3ec80000,0xbf8ec000,0xbffbc000,
0x3ec83fed,0x3f8e3f44,0x3ffb3f44,0xbfd5bfed,0xbffbbfb5,0x3fd53fb5,0xbec83fb5,0xbf8ebfb5,0x3f8ebf44,0x3ffb3fed,0xbfd5bfed,0xbec8bf44,
0xbfffbfb5,0xbfc6bfb5,0xbe493fb5,0x3fa23fb5,0x3f15bf8e,0xbfe2bfd5,0xbff5bfd5,0x3f713f8e,0x3fe23fed,0xbff5bfed,0x3f71bf44,0x3f153f44,
0xbfa23ec8,0xbfffbffb,0x3fc63ffb,0x3e493ec8,0x80003f80,0x3f800000,0x80003f80,0x3f800000,0x80003f80,0x3f800000,0x80003f80,0x3f800000,
0x80003f80,0x3f800000,0x80003f80,0x3f800000,0x80003f80,0x3f800000,0x80003f80,0x3f800000,0x80003f80,0x3f800000,0x8000bf80,0xbf800000,
0x3f353f35,0x3f35bf35,0xbf35bf35,0xbf353f35,0x3f800000,0xbf80,0xbf800000,0x3f80,0x3f35bf35,0xbf35bf35,0xbf353f35,0x3f353f35,
0x80003f80,0x3f800000,0x80003f80,0x3f800000,0x3f800000,0xbf80,0x3f800000,0xbf80,0x8000bf80,0xbf800000,0x8000bf80,0xbf800000,
0xbf800000,0x3f80,0xbf800000,0x3f80,0x80003f80,0x3f800000,0x8000bf80,0xbf800000,0x3f35bf35,0xbf35bf35,0xbf353f35,0x3f353f35,
0xbf800000,0x3f80,0x3f800000,0xbf80,0x3f353f35,0x3f35bf35,0xbf35bf35,0xbf353f35,0x80003f80,0x3f800000,0x80003f80,0x3f800000,
0x8000bf80,0xbf800000,0x8000bf80,0xbf800000,0x80003f80,0x3f800000,0x80003f80,0x3f800000,0x8000bf80,0xbf800000,0x8000bf80,0xbf800000,
0x80003f80,0x3f800000,0x8000bf80,0xbf800000,0xbf35bf35,0xbf353f35,0x3f353f35,0x3f35bf35,0x3f800000,0xbf80,0xbf800000,0x3f80,
0xbf353f35,0x3f353f35,0x3f35bf35,0xbf35bf35,0x80003f80,0x3f800000,0x80003f80,0x3f800000,0xbf800000,0x3f80,0xbf800000,0x3f80,
0x8000bf80,0xbf800000,0x8000bf80,0xbf800000,0x3f800000,0xbf80,0x3f800000,0xbf80,0x80003f80,0x3f800000,0x8000bf80,0xbf800000,
0xbf353f35,0x3f353f35,0x3f35bf35,0xbf35bf35,0xbf800000,0x3f80,0x3f800000,0xbf80,0xbf35bf35,0xbf353f35,0x3f353f35,0x3f35bf35,
0x3f803f80,0x80008000,0x80008000,0xbf80bf80,0x3f803f80,0x80008000,0x80008000,0xbf80bf80,0x3f803f80,0x80008000,0x80008000,0xbf80bf80,
0x3f803f80,0x80008000,0x80008000,0xbf80bf80,0x3f353f80,0x3f358000,0x3f358000,0xbf35bf80,0xbf350000,0x3f353f80,0x3f353f80,0x3f358000,
0xbf35bf80,0xbf358000,0xbf358000,0x3f353f80,0x3f350000,0xbf35bf80,0xbf35bf80,0xbf358000,0x3f80,0x3f808000,0x3f808000,0x8000bf80,
0xbf80,0xbf808000,0xbf808000,0x80003f80,0x3f80,0x3f808000,0x3f808000,0x8000bf80,0xbf80,0xbf808000,0xbf808000,0x80003f80,
0xbf353f80,0x3f358000,0x3f358000,0x3f35bf80,0x3f350000,0x3f35bf80,0x3f35bf80,0xbf358000,0x3f35bf80,0xbf358000,0xbf358000,0xbf353f80,
0xbf350000,0xbf353f80,0xbf353f80,0x3f358000,0xbf803f80,0x80008000,0x80008000,0x3f80bf80,0xbf803f80,0x80008000,0x80008000,0x3f80bf80,
0xbf803f80,0x80008000,0x80008000,0x3f80bf80,0xbf803f80,0x80008000,0x80008000,0x3f80bf80,0xbf353f80,0xbf358000,0xbf358000,0x3f35bf80,
0x3f350000,0xbf353f80,0xbf353f80,0xbf358000,0x3f35bf80,0x3f358000,0x3f358000,0xbf353f80,0xbf350000,0x3f35bf80,0x3f35bf80,0x3f358000,
0x3f80,0xbf808000,0xbf808000,0x8000bf80,0xbf80,0x3f808000,0x3f808000,0x80003f80,0x3f80,0xbf808000,0xbf808000,0x8000bf80,
0xbf80,0x3f808000,0x3f808000,0x80003f80,0x3f353f80,0xbf358000,0xbf358000,0xbf35bf80,0xbf350000,0xbf35bf80,0xbf35bf80,0x3f358000,
0xbf35bf80,0x3f358000,0x3f358000,0x3f353f80,0x3f350000,0x3f353f80,0x3f353f80,0xbf358000,0x3f800000,0x0,0x3f800000,0x0,
0x3f800000,0x0,0x3f800000,0x0,0x3f800000,0x0,0x3f800000,0x0,0x3f800000,0x0,0x3f800000,0x0,
0x3f800000,0x0,0x3f7fb10f,0xbd48fb30,0x3f7ec46d,0xbdc8bd36,0x3f7d3aac,0xbe164083,0x3f7b14be,0xbe47c5c2,0x3f7853f8,0xbe78cfcc,
0x3f74fa0b,0xbe94a031,0x3f710908,0xbeac7cd4,0x3f800000,0x0,0x3f7ec46d,0xbdc8bd36,0x3f7b14be,0xbe47c5c2,0x3f74fa0b,0xbe94a031,
0x3f6c835e,0xbec3ef15,0x3f61c598,0xbef15aea,0x3f54db31,0xbf0e39da,0x3f45e403,0xbf226799,0x3f800000,0x0,0x3f7d3aac,0xbe164083,
0x3f74fa0b,0xbe94a031,0x3f676bd8,0xbedae880,0x3f54db31,0xbf0e39da,0x3f3daef9,0xbf2beb4a,0x3f226799,0xbf45e403,0x3f039c3d,0xbf5b941a,
0x3f800000,0x0,0x3f7b14be,0xbe47c5c2,0x3f6c835e,0xbec3ef15,0x3f54db31,0xbf0e39da,0x3f3504f3,0xbf3504f3,0x3f0e39da,0xbf54db31,
0x3ec3ef15,0xbf6c835e,0x3e47c5c2,0xbf7b14be,0x3f800000,0x0,0x3f7853f8,0xbe78cfcc,0x3f61c598,0xbef15aea,0x3f3daef9,0xbf2beb4a,
0x3f0e39da,0xbf54db31,0x3eac7cd4,0xbf710908,0x3dc8bd36,0xbf7ec46d,0xbe164083,0xbf7d3aac,0x3f800000,0x0,0x3f74fa0b,0xbe94a031,
0x3f54db31,0xbf0e39da,0x3f226799,0xbf45e403,0x3ec3ef15,0xbf6c835e,0x3dc8bd36,0xbf7ec46d,0xbe47c5c2,0xbf7b14be,0xbef15aea,0xbf61c598,
0x3f800000,0x0,0x3f710908,0xbeac7cd4,0x3f45e403,0xbf226799,0x3f039c3d,0xbf5b941a,0x3e47c5c2,0xbf7b14be,0xbe164083,0xbf7d3aac,
0xbef15aea,0xbf61c598,0xbf3daef9,0xbf2beb4a,0x3f800000,0x0,0x3f800000,0x0,0x3f800000,0x0,0x3f800000,0x0,
0x3f800000,0x0,0x3f800000,0x0,0x3f800000,0x0,0x3f800000,0x0,0x3f6c835e,0xbec3ef15,0x3f676bd8,0xbedae880,
0x3f61c598,0xbef15aea,0x3f5b941a,0xbf039c3d,0x3f54db31,0xbf0e39da,0x3f4d9f02,0xbf187fc0,0x3f45e403,0xbf226799,0x3f3daef9,0xbf2beb4a,
0x3f3504f3,0xbf3504f3,0x3f226799,0xbf45e403,0x3f0e39da,0xbf54db31,0x3ef15aea,0xbf61c598,0x3ec3ef15,0xbf6c835e,0x3e94a031,0xbf74fa0b,
0x3e47c5c2,0xbf7b14be,0x3dc8bd36,0xbf7ec46d,0x3ec3ef15,0xbf6c835e,0x3e78cfcc,0xbf7853f8,0x3dc8bd36,0xbf7ec46d,0xbd48fb30,0xbf7fb10f,
0xbe47c5c2,0xbf7b14be,0xbeac7cd4,0xbf710908,0xbef15aea,0xbf61c598,0xbf187fc0,0xbf4d9f02,0x0,0xbf800000,0xbe47c5c2,0xbf7b14be,
0xbec3ef15,0xbf6c835e,0xbf0e39da,0xbf54db31,0xbf3504f3,0xbf3504f3,0xbf54db31,0xbf0e39da,0xbf6c835e,0xbec3ef15,0xbf7b14be,0xbe47c5c2,
0xbec3ef15,0xbf6c835e,0xbf187fc0,0xbf4d9f02,0xbf45e403,0xbf226799,0xbf676bd8,0xbedae880,0xbf7b14be,0xbe47c5c2,0xbf7fb10f,0x3d48fb30,
0xbf74fa0b,0x3e94a031,0xbf5b941a,0x3f039c3d,0xbf3504f3,0xbf3504f3,0xbf61c598,0xbef15aea,0xbf7b14be,0xbe47c5c2,0xbf7ec46d,0x3dc8bd36,
0xbf6c835e,0x3ec3ef15,0xbf45e403,0x3f226799,0xbf0e39da,0x3f54db31,0xbe94a031,0x3f74fa0b,0xbf6c835e,0xbec3ef15,0xbf7fb10f,0xbd48fb30,
0xbf74fa0b,0x3e94a031,0xbf4d9f02,0x3f187fc0,0xbf0e39da,0x3f54db31,0xbe78cfcc,0x3f7853f8,0x3dc8bd36,0x3f7ec46d,0x3edae880,0x3f676bd8,
0x80003f80,0x3f800000,0x3f800000,0xbf80,0x3ec43f6d,0x3f6dbec4,0x3f6dbec4,0xbec4bf6d,0x3f353f35,0x3f35bf35,0x3f35bf35,0xbf35bf35,
0x3f6d3ec4,0x3ec4bf6d,0x3ec4bf6d,0xbf6dbec4,0x80003f80,0x3f800000,0xbf800000,0x3f80,0x3f6d3ec4,0x3ec4bf6d,0xbec43f6d,0x3f6d3ec4,
0x3f35bf35,0xbf35bf35,0x3f353f35,0x3f35bf35,0xbec4bf6d,0xbf6d3ec4,0x3f6dbec4,0xbec4bf6d,0x80003f80,0x3f800000,0x3f800000,0xbf80,
0x3f6dbec4,0xbec4bf6d,0xbec4bf6d,0xbf6d3ec4,0xbf35bf35,0xbf353f35,0xbf353f35,0x3f353f35,0xbec43f6d,0x3f6d3ec4,0x3f6d3ec4,0x3ec4bf6d,
0x80003f80,0x3f800000,0xbf800000,0x3f80,0x3ec4bf6d,0xbf6dbec4,0x3f6d3ec4,0x3ec4bf6d,0xbf353f35,0x3f353f35,0xbf35bf35,0xbf353f35,
0x3f6dbec4,0xbec4bf6d,0x3ec43f6d,0x3f6dbec4,0x80003f80,0x3f800000,0x3f800000,0xbf80,0xbec4bf6d,0xbf6d3ec4,0xbf6d3ec4,0x3ec43f6d,
0x3f353f35,0x3f35bf35,0x3f35bf35,0xbf35bf35,0xbf6dbec4,0xbec43f6d,0xbec43f6d,0x3f6d3ec4,0x80003f80,0x3f800000,0xbf800000,0x3f80,
0xbf6dbec4,0xbec43f6d,0x3ec4bf6d,0xbf6dbec4,0x3f35bf35,0xbf35bf35,0x3f353f35,0x3f35bf35,0x3ec43f6d,0x3f6dbec4,0xbf6d3ec4,0x3ec43f6d,
0x80003f80,0x3f800000,0x3f800000,0xbf80,0xbf6d3ec4,0x3ec43f6d,0x3ec43f6d,0x3f6dbec4,0xbf35bf35,0xbf353f35,0xbf353f35,0x3f353f35,
0x3ec4bf6d,0xbf6dbec4,0xbf6dbec4,0xbec43f6d,0x80003f80,0x3f800000,0xbf800000,0x3f80,0xbec43f6d,0x3f6d3ec4,0xbf6dbec4,0xbec43f6d,
0xbf353f35,0x3f353f35,0xbf35bf35,0xbf353f35,0xbf6d3ec4,0x3ec43f6d,0xbec4bf6d,0xbf6d3ec4,0x3f803f80,0x80008000,0x80008000,0xbf80bf80,
0x3f803f80,0x80008000,0x80008000,0xbf80bf80,0x3f803f80,0x80008000,0x80008000,0xbf80bf80,0x3f803f80,0x80008000,0x80008000,0xbf80bf80,
0x3ec43f6d,0x3f6d3ec4,0x3f6d3ec4,0xbec4bf6d,0xbf6dbec4,0x3ec43f6d,0x3ec43f6d,0x3f6d3ec4,0xbec4bf6d,0xbf6dbec4,0xbf6dbec4,0x3ec43f6d,
0x3f6d3ec4,0xbec4bf6d,0xbec4bf6d,0xbf6dbec4,0xbf353f35,0x3f353f35,0x3f353f35,0x3f35bf35,0x3f35bf35,0xbf35bf35,0xbf35bf35,0xbf353f35,
0xbf353f35,0x3f353f35,0x3f353f35,0x3f35bf35,0x3f35bf35,0xbf35bf35,0xbf35bf35,0xbf353f35,0xbf6d3ec4,0xbec43f6d,0xbec43f6d,0x3f6dbec4,
0xbec43f6d,0x3f6dbec4,0x3f6dbec4,0x3ec4bf6d,0x3f6dbec4,0x3ec4bf6d,0x3ec4bf6d,0xbf6d3ec4,0x3ec4bf6d,0xbf6d3ec4,0xbf6d3ec4,0xbec43f6d,
0x0,0xbf803f80,0xbf803f80,0x80008000,0x0,0xbf803f80,0xbf803f80,0x80008000,0x0,0xbf803f80,0xbf803f80,0x80008000,
0x0,0xbf803f80,0xbf803f80,0x80008000,0x3f6dbec4,0xbec43f6d,0xbec43f6d,0xbf6d3ec4,0x3ec4bf6d,0x3f6dbec4,0x3f6dbec4,0xbec43f6d,
0xbf6d3ec4,0x3ec4bf6d,0x3ec4bf6d,0x3f6dbec4,0xbec43f6d,0xbf6d3ec4,0xbf6d3ec4,0x3ec4bf6d,0x3f35bf35,0x3f353f35,0x3f353f35,0xbf353f35,
0xbf353f35,0xbf35bf35,0xbf35bf35,0x3f35bf35,0x3f35bf35,0x3f353f35,0x3f353f35,0xbf353f35,0xbf353f35,0xbf35bf35,0xbf35bf35,0x3f35bf35,
0xbec4bf6d,0x3f6d3ec4,0x3f6d3ec4,0x3ec43f6d,0x3f6d3ec4,0x3ec43f6d,0x3ec43f6d,0xbf6dbec4,0x3ec43f6d,0xbf6dbec4,0xbf6dbec4,0xbec4bf6d,
0xbf6dbec4,0xbec4bf6d,0xbec4bf6d,0x3f6d3ec4,0x3f800000,0x0,0x3f7fec43,0xbcc90ab0,0x3f7fb10f,0xbd48fb30,0x3f7f4e6d,0xbd96a905,
0x3f7ec46d,0xbdc8bd36,0x3f7e1324,0xbdfab273,0x3f7d3aac,0xbe164083,0x3f7c3b28,0xbe2f10a2,0x3f800000,0x0,0x3f7f4e6d,0xbd96a905,
0x3f7d3aac,0xbe164083,0x3f79c79d,0xbe605c13,0x3f74fa0b,0xbe94a031,0x3f6ed89e,0xbeb8442a,0x3f676bd8,0xbedae880,0x3f5ebe05,0xbefc5d27,
0x3f800000,0x0,0x3f7e1324,0xbdfab273,0x3f7853f8,0xbe78cfcc,0x3f6ed89e,0xbeb8442a,0x3f61c598,0xbef15aea,0x3f514d3d,0xbf13682a,
0x3f3daef9,0xbf2beb4a,0x3f273656,0xbf41d870,0x3f800000,0x0,0x3f7c3b28,0xbe2f10a2,0x3f710908,0xbeac7cd4,0x3f5ebe05,0xbefc5d27,
0x3f45e403,0xbf226799,0x3f273656,0xbf41d870,0x3f039c3d,0xbf5b941a,0x3eb8442a,0xbf6ed89e,0x3f800000,0x0,0x3f79c79d,0xbe605c13,
0x3f676bd8,0xbedae880,0x3f49d112,0xbf1d7fd1,0x3f226799,0xbf45e403,0x3ee63375,0xbf64aa59,0x3e78cfcc,0xbf7853f8,0x3cc90ab0,0xbf7fec43,
0x3f800000,0x0,0x3f76ba07,0xbe888e93,0x3f5b941a,0xbf039c3d,0x3f3085bb,0xbf396842,0x3ef15aea,0xbf61c598,0x3e605c13,0xbf79c79d,
0xbd48fb30,0xbf7fb10f,0xbea09ae5,0xbf731447,0x3f800000,0x0,0x3f731447,0xbea09ae5,0x3f4d9f02,0xbf187fc0,0x3f13682a,0xbf514d3d,
0x3e94a031,0xbf74fa0b,0xbcc90ab0,0xbf7fec43,0xbeac7cd4,0xbf710908,0xbf1d7fd1,0xbf49d112,0x3f800000,0x0,0x3f6ed89e,0xbeb8442a,
0x3f3daef9,0xbf2beb4a,0x3ee63375,0xbf64aa59,0x3dc8bd36,0xbf7ec46d,0xbe888e93,0xbf76ba07,0xbf187fc0,0xbf4d9f02,0xbf584853,0xbf08f59b,
0x3f7b14be,0xbe47c5c2,0x3f79c79d,0xbe605c13,0x3f7853f8,0xbe78cfcc,0x3f76ba07,0xbe888e93,0x3f74fa0b,0xbe94a031,0x3f731447,0xbea09ae5,
0x3f710908,0xbeac7cd4,0x3f6ed89e,0xbeb8442a,0x3f54db31,0xbf0e39da,0x3f49d112,0xbf1d7fd1,0x3f3daef9,0xbf2beb4a,0x3f3085bb,0xbf396842,
0x3f226799,0xbf45e403,0x3f13682a,0xbf514d3d,0x3f039c3d,0xbf5b941a,0x3ee63375,0xbf64aa59,0x3f0e39da,0xbf54db31,0x3ee63375,0xbf64aa59,
0x3eac7cd4,0xbf710908,0x3e605c13,0xbf79c79d,0x3dc8bd36,0xbf7ec46d,0xbcc90ab0,0xbf7fec43,0xbe164083,0xbf7d3aac,0xbe888e93,0xbf76ba07,
0x3e47c5c2,0xbf7b14be,0x3cc90ab0,0xbf7fec43,0xbe164083,0xbf7d3aac,0xbea09ae5,0xbf731447,0xbef15aea,0xbf61c598,0xbf1d7fd1,0xbf49d112,
0xbf3daef9,0xbf2beb4a,0xbf584853,0xbf08f59b,0xbe47c5c2,0xbf7b14be,0xbecf7bca,0xbf6a09a7,0xbf187fc0,0xbf4d9f02,0xbf41d870,0xbf273656,
0xbf61c598,0xbef15aea,0xbf76ba07,0xbe888e93,0xbf7fb10f,0xbd48fb30,0xbf7c3b28,0x3e2f10a2,0xbf0e39da,0xbf54db31,0xbf41d870,0xbf273656,
0xbf676bd8,0xbedae880,0xbf7c3b28,0xbe2f10a2,0xbf7ec46d,0x3dc8bd36,0xbf6ed89e,0x3eb8442a,0xbf4d9f02,0x3f187fc0,0xbf1d7fd1,0x3f49d112,
0xbf54db31,0xbf0e39da,0xbf76ba07,0xbe888e93,0xbf7fb10f,0x3d48fb30,0xbf6ed89e,0x3eb8442a,0xbf45e403,0x3f226799,0xbf08f59b,0x3f584853,
0xbe78cfcc,0x3f7853f8,0x3d96a905,0x3f7f4e6d,0xbf7b14be,0xbe47c5c2,0xbf7c3b28,0x3e2f10a2,0xbf5b941a,0x3f039c3d,0xbf1d7fd1,0x3f49d112,
0xbe94a031,0x3f74fa0b,0x3d96a905,0x3f7f4e6d,0x3edae880,0x3f676bd8,0x3f396842,0x3f3085bb,0x80003f80,0x80003f80,0x80003f80,0x80003f80,
0x80003f80,0x80003f80,0x80003f80,0x80003f80,0x80003f80,0x80003f80,0x80003f80,0x80003f80,0x80003f80,0x80003f80,0x80003f80,0x80003f80,
0x3f800000,0x3f800000,0x3f800000,0x3f800000,0x3f800000,0x3f800000,0x3f800000,0x3f800000,0x3f800000,0x3f800000,0x3f800000,0x3f800000,
0x3f800000,0x3f800000,0x3f800000,0x3f800000,0x80003f80,0x3f353f35,0x80003f80,0x3f353f35,0x3f800000,0x3f35bf35,0x3f800000,0x3f35bf35,
0x8000bf80,0xbf35bf35,0x8000bf80,0xbf35bf35,0xbf800000,0xbf353f35,0xbf800000,0xbf353f35,0x3f800000,0x3f35bf35,0x3f800000,0x3f35bf35,
0xbf80,0xbf35bf35,0xbf80,0xbf35bf35,0xbf800000,0xbf353f35,0xbf800000,0xbf353f35,0x3f80,0x3f353f35,0x3f80,0x3f353f35,
0x80003f80,0x3f800000,0x80003f80,0x3f800000,0x8000bf80,0xbf800000,0x8000bf80,0xbf800000,0x80003f80,0x3f800000,0x80003f80,0x3f800000,
0x8000bf80,0xbf800000,0x8000bf80,0xbf800000,0x3f800000,0xbf80,0x3f800000,0xbf80,0xbf800000,0x3f80,0xbf800000,0x3f80,
0x3f800000,0xbf80,0x3f800000,0xbf80,0xbf800000,0x3f80,0xbf800000,0x3f80,0x80003f80,0x3f35bf35,0x80003f80,0x3f35bf35,
0xbf800000,0x3f353f35,0xbf800000,0x3f353f35,0x8000bf80,0xbf353f35,0x8000bf80,0xbf353f35,0x3f800000,0xbf35bf35,0x3f800000,0xbf35bf35,
0x3f800000,0xbf35bf35,0x3f800000,0xbf35bf35,0x3f80,0x3f35bf35,0x3f80,0x3f35bf35,0xbf800000,0x3f353f35,0xbf800000,0x3f353f35,
0xbf80,0xbf353f35,0xbf80,0xbf353f35,0x80003f80,0x3ec43f6d,0x8000bf80,0xbec4bf6d,0x3f353f35,0x3f6d3ec4,0xbf35bf35,0xbf6dbec4,
0x3f800000,0x3f6dbec4,0xbf800000,0xbf6d3ec4,0x3f35bf35,0x3ec4bf6d,0xbf353f35,0xbec43f6d,0x3f800000,0x3f6dbec4,0xbf800000,0xbf6d3ec4,
0x3f35bf35,0x3ec4bf6d,0xbf353f35,0xbec43f6d,0xbf80,0xbec4bf6d,0x3f80,0x3ec43f6d,0xbf35bf35,0xbf6dbec4,0x3f353f35,0x3f6d3ec4,
0x80003f80,0x3f6d3ec4,0x8000bf80,0xbf6dbec4,0x3f35bf35,0xbec4bf6d,0xbf353f35,0x3ec43f6d,0xbf800000,0xbec43f6d,0x3f800000,0x3ec4bf6d,
0x3f353f35,0x3f6dbec4,0xbf35bf35,0xbf6d3ec4,0x3f800000,0x3ec4bf6d,0xbf800000,0xbec43f6d,0xbf35bf35,0xbf6d3ec4,0x3f353f35,0x3f6dbec4,
0x3f80,0x3f6d3ec4,0xbf80,0xbf6dbec4,0x3f35bf35,0xbec4bf6d,0xbf353f35,0x3ec43f6d,0x80003f80,0x3f6dbec4,0x8000bf80,0xbf6d3ec4,
0xbf35bf35,0xbec43f6d,0x3f353f35,0x3ec4bf6d,0x3f800000,0xbec4bf6d,0xbf800000,0x3ec43f6d,0xbf353f35,0x3f6d3ec4,0x3f35bf35,0xbf6dbec4,
0x3f800000,0xbec4bf6d,0xbf800000,0x3ec43f6d,0xbf353f35,0x3f6d3ec4,0x3f35bf35,0xbf6dbec4,0xbf80,0xbf6d3ec4,0x3f80,0x3f6dbec4,
0x3f353f35,0x3ec4bf6d,0xbf35bf35,0xbec43f6d,0x80003f80,0x3ec4bf6d,0x8000bf80,0xbec43f6d,0xbf353f35,0x3f6dbec4,0x3f35bf35,0xbf6d3ec4,
0xbf800000,0x3f6d3ec4,0x3f800000,0xbf6dbec4,0xbf35bf35,0x3ec43f6d,0x3f353f35,0xbec4bf6d,0x3f800000,0xbf6dbec4,0xbf800000,0x3f6d3ec4,
0x3f353f35,0xbec4bf6d,0xbf35bf35,0x3ec43f6d,0x3f80,0x3ec4bf6d,0xbf80,0xbec43f6d,0xbf353f35,0x3f6dbec4,0x3f35bf35,0xbf6d3ec4,
0x80003f80,0x8000bf80,0x80003f80,0x8000bf80,0x80003f80,0x8000bf80,0x80003f80,0x8000bf80,0x80003f80,0x8000bf80,0x80003f80,0x8000bf80,
0x80003f80,0x8000bf80,0x80003f80,0x8000bf80,0x3f800000,0xbf800000,0x3f800000,0xbf800000,0x3f800000,0xbf800000,0x3f800000,0xbf800000,
0x3f800000,0xbf800000,0x3f800000,0xbf800000,0x3f800000,0xbf800000,0x3f800000,0xbf800000,0x80003f80,0xbf35bf35,0x80003f80,0xbf35bf35,
0x3f800000,0xbf353f35,0x3f800000,0xbf353f35,0x8000bf80,0x3f353f35,0x8000bf80,0x3f353f35,0xbf800000,0x3f35bf35,0xbf800000,0x3f35bf35,
0x3f800000,0xbf353f35,0x3f800000,0xbf353f35,0xbf80,0x3f353f35,0xbf80,0x3f353f35,0xbf800000,0x3f35bf35,0xbf800000,0x3f35bf35,
0x3f80,0xbf35bf35,0x3f80,0xbf35bf35,0x80003f80,0xbf800000,0x80003f80,0xbf800000,0x8000bf80,0x3f800000,0x8000bf80,0x3f800000,
0x80003f80,0xbf800000,0x80003f80,0xbf800000,0x8000bf80,0x3f800000,0x8000bf80,0x3f800000,0x3f800000,0x3f80,0x3f800000,0x3f80,
0xbf800000,0xbf80,0xbf800000,0xbf80,0x3f800000,0x3f80,0x3f800000,0x3f80,0xbf800000,0xbf80,0xbf800000,0xbf80,
0x80003f80,0xbf353f35,0x80003f80,0xbf353f35,0xbf800000,0xbf35bf35,0xbf800000,0xbf35bf35,0x8000bf80,0x3f35bf35,0x8000bf80,0x3f35bf35,
0x3f800000,0x3f353f35,0x3f800000,0x3f353f35,0x3f800000,0x3f353f35,0x3f800000,0x3f353f35,0x3f80,0xbf353f35,0x3f80,0xbf353f35,
0xbf800000,0xbf35bf35,0xbf800000,0xbf35bf35,0xbf80,0x3f35bf35,0xbf80,0x3f35bf35,0x80003f80,0xbec4bf6d,0x8000bf80,0x3ec43f6d,
0x3f353f35,0xbf6dbec4,0xbf35bf35,0x3f6d3ec4,0x3f800000,0xbf6d3ec4,0xbf800000,0x3f6dbec4,0x3f35bf35,0xbec43f6d,0xbf353f35,0x3ec4bf6d,
0x3f800000,0xbf6d3ec4,0xbf800000,0x3f6dbec4,0x3f35bf35,0xbec43f6d,0xbf353f35,0x3ec4bf6d,0xbf80,0x3ec43f6d,0x3f80,0xbec4bf6d,
0xbf35bf35,0x3f6d3ec4,0x3f353f35,0xbf6dbec4,0x80003f80,0xbf6dbec4,0x8000bf80,0x3f6d3ec4,0x3f35bf35,0x3ec43f6d,0xbf353f35,0xbec4bf6d,
0xbf800000,0x3ec4bf6d,0x3f800000,0xbec43f6d,0x3f353f35,0xbf6d3ec4,0xbf35bf35,0x3f6dbec4,0x3f800000,0xbec43f6d,0xbf800000,0x3ec4bf6d,
0xbf35bf35,0x3f6dbec4,0x3f353f35,0xbf6d3ec4,0x3f80,0xbf6dbec4,0xbf80,0x3f6d3ec4,0x3f35bf35,0x3ec43f6d,0xbf353f35,0xbec4bf6d,
0x80003f80,0xbf6d3ec4,0x8000bf80,0x3f6dbec4,0xbf35bf35,0x3ec4bf6d,0x3f353f35,0xbec43f6d,0x3f800000,0x3ec43f6d,0xbf800000,0xbec4bf6d,
0xbf353f35,0xbf6dbec4,0x3f35bf35,0x3f6d3ec4,0x3f800000,0x3ec43f6d,0xbf800000,0xbec4bf6d,0xbf353f35,0xbf6dbec4,0x3f35bf35,0x3f6d3ec4,
0xbf80,0x3f6dbec4,0x3f80,0xbf6d3ec4,0x3f353f35,0xbec43f6d,0xbf35bf35,0x3ec4bf6d,0x80003f80,0xbec43f6d,0x8000bf80,0x3ec4bf6d,
0xbf353f35,0xbf6d3ec4,0x3f35bf35,0x3f6dbec4,0xbf800000,0xbf6dbec4,0x3f800000,0x3f6d3ec4,0xbf35bf35,0xbec4bf6d,0x3f353f35,0x3ec43f6d,
0x3f800000,0x3f6d3ec4,0xbf800000,0xbf6dbec4,0x3f353f35,0x3ec43f6d,0xbf35bf35,0xbec4bf6d,0x3f80,0xbec43f6d,0xbf80,0x3ec4bf6d,
0xbf353f35,0xbf6d3ec4,0x3f35bf35,0x3f6dbec4,
};
constexpr int TB_F = 0, TB_E = 512, TB_P2 = 1024;

enum { C_EP = 0, C_Z1 = 32, C_Z2 = 96, C_H3 = 128, C_U = 160, C_X = 288, C_TOTAL = 512 };
struct Scratch {
  unsigned cnt[C_TOTAL];
  uint32_t moda[8 * 2 * D_];
  uint32_t mod[4 * D_ + 256];
  uint32_t z1[120 * 5120];
  uint32_t z2[128 * 4800];
  uint8_t h3[32 * 18 * 4096];
  uint8_t u[72 * D_ * 128];
};
__device__ __align__(1024) Scratch g_s;

#define HOLDA 5
#define GOAT 0
#define H3W 0
#define X1K 10
#define PEEK 1
#ifndef NV1
#define NV1 12
#endif
#ifndef NV2
#define NV2 20
#endif
#define GDEP 0
#define TRK0 50
#define W0N 3
#define TRKC 350
#define J2 6
#define HD1 150
#define STRESS 0
#define KNOB0 0

#define FAILCNT(k) do {} while (0)
#define CK(k) do {} while (0)
#define CKX(k) do {} while (0)
#define TS(k) do {} while (0)
#define TSC(k) do {} while (0)
struct Maps { CUtensorMap z1, z2[2], w1a, w1b, h3, w2, wf[4], wm; };
struct Params {
  const __nv_bfloat16 *x, *c, *wmod;
  Scratch* s;
  const uint4* tab;
  const __nv_bfloat16 *wr, *wi, *w1, *w2, *b1, *b2;
  uint32_t* out;
};

__device__ __forceinline__ uint32_t smem_u32(const void* p) { return (uint32_t)__cvta_generic_to_shared(p); }
__device__ __forceinline__ void mbar_init(uint32_t b, int c) { asm volatile("mbarrier.init.shared::cta.b64 [%0], %1;" ::"r"(b), "r"(c)); }
__device__ __forceinline__ void mbar_expect(uint32_t b, int bytes) { asm volatile("mbarrier.arrive.expect_tx.shared::cta.b64 _, [%0], %1;" ::"r"(b), "r"(bytes) : "memory"); }
__device__ __forceinline__ void mbar_arrive(uint32_t b) { asm volatile("mbarrier.arrive.shared::cta.b64 _, [%0];" ::"r"(b) : "memory"); }
#define MBAR_WAIT(SEM)                                                                                                         \
  asm volatile("{\n.reg .pred p;\n.reg .u32 it;\nmov.u32 it, 0;\nW:\nmbarrier.try_wait.parity" SEM ".shared::cta.b64 p, [%0], %1;\n" \
               "@p bra.uni D;\nadd.u32 it, it, 1;\nsetp.lt.u32 p, it, 0x400000;\n@p bra.uni W;\ntrap;\nD:\n}" ::"r"(b), "r"(ph) : "memory")
__device__ __forceinline__ void mbar_wait(uint32_t b, int ph) { MBAR_WAIT(""); }
__device__ __forceinline__ uint32_t mbar_test(uint32_t b, int ph) {
  uint32_t ok;
  asm volatile("{\n.reg .pred p;\nmbarrier.test_wait.parity.shared::cta.b64 p, [%1], %2;\nselp.u32 %0, 1, 0, p;\n}\n" : "=r"(ok) : "r"(b), "r"(ph) : "memory");
  return ok;
}
__device__ __forceinline__ void tma2d(uint32_t dst, const CUtensorMap* m, int c0, int c1, uint32_t bar) {
  asm volatile("cp.async.bulk.tensor.2d.shared::cluster.global.mbarrier::complete_tx::bytes [%0], [%1, {%3, %4}], [%2];" ::"r"(dst), "l"(m), "r"(bar), "r"(c0), "r"(c1) : "memory");
}
__device__ __forceinline__ uint64_t pol_ef() { uint64_t p; asm("createpolicy.fractional.L2::evict_first.b64 %0, 1.0;" : "=l"(p)); return p; }
__device__ __forceinline__ void tma3d_ef(uint32_t dst, const CUtensorMap* m, int c1, int c2, uint32_t bar) {
  asm volatile("cp.async.bulk.tensor.3d.shared::cluster.global.mbarrier::complete_tx::bytes.L2::cache_hint [%0], [%1, {%3, %4, %5}], [%2], %6;" ::"r"(dst), "l"(m), "r"(bar), "r"(0), "r"(c1), "r"(c2), "l"(pol_ef()) : "memory");
}
__device__ __forceinline__ void tma4d_ef(uint32_t dst, const CUtensorMap* m, int c1, int c2, int c3, uint32_t bar) {
  asm volatile("cp.async.bulk.tensor.4d.shared::cluster.global.mbarrier::complete_tx::bytes.L2::cache_hint [%0], [%1, {%3, %7, %4, %5}], [%2], %6;" ::"r"(dst), "l"(m), "r"(bar), "r"(0), "r"(c2), "r"(c3), "l"(pol_ef()), "r"(c1) : "memory");
}
__device__ __forceinline__ void bulk_ld(uint32_t dst, const void* src, int bytes, uint32_t bar) {
  asm volatile("cp.async.bulk.shared::cluster.global.mbarrier::complete_tx::bytes [%0], [%1], %2, [%3];" ::"r"(dst), "l"(src), "r"(bytes), "r"(bar) : "memory");
}
__device__ __forceinline__ void bulk_st(void* dst, uint32_t src, int bytes) {
  asm volatile("cp.async.bulk.global.shared::cta.bulk_group [%0], [%1], %2;" ::"l"(dst), "r"(src), "r"(bytes) : "memory");
}
__device__ __forceinline__ void tma_st2d(const CUtensorMap* m, uint32_t src, int c0, int c1) {
  asm volatile("cp.async.bulk.tensor.2d.global.shared::cta.bulk_group [%0, {%2, %3}], [%1];" ::"l"(m), "r"(src), "r"(c0), "r"(c1) : "memory");
}
__device__ __forceinline__ void tma_st3d(const CUtensorMap* m, uint32_t src, int c0, int c1, int c2) {
  asm volatile("cp.async.bulk.tensor.3d.global.shared::cta.bulk_group [%0, {%2, %3, %4}], [%1];" ::"l"(m), "r"(src), "r"(c0), "r"(c1), "r"(c2) : "memory");
}
__device__ __forceinline__ void bulk_commit_wait_read() {
  asm volatile("cp.async.bulk.commit_group;" ::: "memory");
  asm volatile("cp.async.bulk.wait_group.read 0;" ::: "memory");
}
__device__ __forceinline__ void bulk_commit_wait() {
  asm volatile("cp.async.bulk.commit_group;" ::: "memory");
  asm volatile("cp.async.bulk.wait_group 0;" ::: "memory");
}
__device__ __forceinline__ void prefetch_l2(const void* p, int bytes) {
  asm volatile("cp.async.bulk.prefetch.L2.global [%0], %1;" ::"l"(p), "r"(bytes) : "memory");
}
__device__ __forceinline__ void wg_fence() { asm volatile("wgmma.fence.sync.aligned;" ::: "memory"); }
__device__ __forceinline__ void wg_commit() { asm volatile("wgmma.commit_group.sync.aligned;" ::: "memory"); }
template <int N> __device__ __forceinline__ void wg_wait() { asm volatile("wgmma.wait_group.sync.aligned %0;" ::"n"(N) : "memory"); }
template <int N> __device__ __forceinline__ void reg_fence(float (&d)[N]) {
#pragma unroll
  for (int i = 0; i < N; i++) asm volatile("" : "+f"(d[i])::"memory");
}
__device__ __forceinline__ void fence_async_smem() { asm volatile("fence.proxy.async.shared::cta;" ::: "memory"); }
__device__ __forceinline__ void fence_async_glb() { asm volatile("fence.proxy.async.global;" ::: "memory"); }
__device__ __forceinline__ uint32_t ld_rlx(const void* p) { uint32_t v; asm volatile("ld.relaxed.gpu.global.b32 %0, [%1];" : "=r"(v) : "l"(p) : "memory"); return v; }
__device__ __forceinline__ uint2 ld_rlx2(const void* p) { uint2 v; asm volatile("ld.relaxed.gpu.global.v2.b32 {%0,%1}, [%2];" : "=r"(v.x), "=r"(v.y) : "l"(p) : "memory"); return v; }
__device__ __forceinline__ uint4 ld_rlx4(const void* p) { uint4 v; asm volatile("ld.relaxed.gpu.global.v4.b32 {%0,%1,%2,%3}, [%4];" : "=r"(v.x), "=r"(v.y), "=r"(v.z), "=r"(v.w) : "l"(p) : "memory"); return v; }
__device__ __forceinline__ uint32_t ld_nc(const void* p) { uint32_t v; asm volatile("ld.global.nc.L1::no_allocate.b32 %0, [%1];" : "=r"(v) : "l"(p) : "memory"); return v; }
__device__ __forceinline__ uint4 ld_nc4(const void* p) { uint4 v; asm volatile("ld.global.nc.v4.b32 {%0,%1,%2,%3}, [%4];" : "=r"(v.x), "=r"(v.y), "=r"(v.z), "=r"(v.w) : "l"(p) : "memory"); return v; }
__device__ __forceinline__ uint32_t lds(uint32_t a) { uint32_t v; asm volatile("ld.shared.b32 %0, [%1];" : "=r"(v) : "r"(a) : "memory"); return v; }
__device__ __forceinline__ uint2 lds2(uint32_t a) { uint2 v; asm volatile("ld.shared.v2.b32 {%0,%1}, [%2];" : "=r"(v.x), "=r"(v.y) : "r"(a) : "memory"); return v; }
__device__ __forceinline__ void lds2_if(int on, uint2& v, uint32_t a) { asm volatile("{\n.reg .pred p;\nsetp.ne.u32 p, %3, 0;\n@p ld.shared.v2.b32 {%0,%1}, [%2];\n}" : "+r"(v.x), "+r"(v.y) : "r"(a), "r"(on) : "memory"); }
__device__ __forceinline__ uint4 lds4(uint32_t a) { uint4 v; asm volatile("ld.shared.v4.b32 {%0,%1,%2,%3}, [%4];" : "=r"(v.x), "=r"(v.y), "=r"(v.z), "=r"(v.w) : "r"(a) : "memory"); return v; }
__device__ __forceinline__ float lds_bf(uint32_t a) { uint32_t v; asm volatile("ld.shared.u16 %0, [%1];" : "=r"(v) : "r"(a) : "memory"); return __uint_as_float(v << 16); }
__device__ __forceinline__ void sts(uint32_t a, uint32_t v) { asm volatile("st.shared.b32 [%0], %1;" ::"r"(a), "r"(v) : "memory"); }
__device__ __forceinline__ void sts2(uint32_t a, uint32_t v0, uint32_t v1) { asm volatile("st.shared.v2.b32 [%0], {%1,%2};" ::"r"(a), "r"(v0), "r"(v1) : "memory"); }
__device__ __forceinline__ void sts4(uint32_t a, uint32_t v0, uint32_t v1, uint32_t v2, uint32_t v3) { asm volatile("st.shared.v4.b32 [%0], {%1,%2,%3,%4};" ::"r"(a), "r"(v0), "r"(v1), "r"(v2), "r"(v3) : "memory"); }
__device__ __forceinline__ void bar_sync(int id, int n) { asm volatile("bar.sync %0, %1;" ::"r"(id), "r"(n) : "memory"); }
__device__ __forceinline__ void bar_arrive(int id, int n) { asm volatile("bar.arrive %0, %1;" ::"r"(id), "r"(n) : "memory"); }
__device__ __forceinline__ void red_add(unsigned* p, unsigned v) { asm volatile("red.relaxed.gpu.global.add.u32 [%0], %1;" ::"l"(p), "r"(v) : "memory"); }
__device__ __forceinline__ bool any(bool p) { return __any_sync(0xffffffffu, p); }
__device__ __forceinline__ void pause(unsigned clks) {
  asm volatile("{\n.reg .pred p;\n.reg .u32 a, b;\nmov.u32 a, %%clock;\nW:\nmov.u32 b, %%clock;\nsub.u32 b, b, a;\nsetp.lt.s32 p, b, %0;\n@p bra.uni W;\n}" ::"r"(clks) : "memory");
}
__device__ __forceinline__ void red_bf16x8(uint32_t* p, uint32_t a, uint32_t b, uint32_t c, uint32_t d) {
  asm volatile("red.relaxed.gpu.global.add.noftz.v4.bf16x2 [%0], {%1,%2,%3,%4};" ::"l"(p), "r"(a), "r"(b), "r"(c), "r"(d) : "memory");
}
__device__ __forceinline__ void red_bf16x4(uint32_t* p, uint32_t a, uint32_t b) {
  asm volatile("red.relaxed.gpu.global.add.noftz.v2.bf16x2 [%0], {%1,%2};" ::"l"(p), "r"(a), "r"(b) : "memory");
}
constexpr int SPIN_MAX = 1 << 20;
__device__ __forceinline__ uint32_t ld_acq(const void* p) { uint32_t v; asm volatile("ld.acquire.gpu.global.b32 %0, [%1];" : "=r"(v) : "l"(p) : "memory"); return v; }
template <bool ACQ = false> __device__ __forceinline__ void wait_cnt(const unsigned* p, unsigned target) {
  int it = 0;
  while (any((int)((ACQ ? ld_acq(p) : ld_rlx(p)) - target) < 0) && ++it < SPIN_MAX) {}
}
__device__ __forceinline__ uint32_t pack_bf16(float lo, float hi) { uint32_t r; asm("cvt.rn.bf16x2.f32 %0, %1, %2;" : "=r"(r) : "f"(hi), "f"(lo)); return r; }
__device__ __forceinline__ float bf_lo(uint32_t v) { return __uint_as_float(v << 16); }
__device__ __forceinline__ float bf_hi(uint32_t v) { return __uint_as_float(v & 0xffff0000u); }
__device__ __forceinline__ uint32_t hadd2(uint32_t a, uint32_t b) { uint32_t r; asm("add.rn.bf16x2 %0, %1, %2;" : "=r"(r) : "r"(a), "r"(b)); return r; }
__device__ __forceinline__ uint32_t hmul2(uint32_t a, uint32_t b) { uint32_t r; asm("mul.rn.bf16x2 %0, %1, %2;" : "=r"(r) : "r"(a), "r"(b)); return r; }
__device__ __forceinline__ uint32_t hfma2(uint32_t a, uint32_t b, uint32_t c) { uint32_t r; asm("fma.rn.bf16x2 %0, %1, %2, %3;" : "=r"(r) : "r"(a), "r"(b), "r"(c)); return r; }
__device__ __forceinline__ float rbf(float x) { uint32_t r; asm("cvt.rn.bf16x2.f32 %0, %1, %2;" : "=r"(r) : "f"(x), "f"(0.0f)); return __uint_as_float(r); }
__device__ __forceinline__ void stmatrix4(uint32_t a, uint32_t r0, uint32_t r1, uint32_t r2, uint32_t r3) {
  asm volatile("stmatrix.sync.aligned.m8n8.x4.shared.b16 [%0], {%1,%2,%3,%4};" ::"r"(a), "r"(r0), "r"(r1), "r"(r2), "r"(r3) : "memory");
}
__device__ __forceinline__ void stmatrix2(uint32_t a, uint32_t r0, uint32_t r1) {
  asm volatile("stmatrix.sync.aligned.m8n8.x2.shared.b16 [%0], {%1,%2};" ::"r"(a), "r"(r0), "r"(r1) : "memory");
}
__device__ __forceinline__ void stmatrix4t(uint32_t a, uint32_t r0, uint32_t r1, uint32_t r2, uint32_t r3) {
  asm volatile("stmatrix.sync.aligned.m8n8.x4.trans.shared.b16 [%0], {%1,%2,%3,%4};" ::"r"(a), "r"(r0), "r"(r1), "r"(r2), "r"(r3) : "memory");
}
__device__ __forceinline__ uint32_t movm(uint32_t a) { uint32_t r; asm("movmatrix.sync.aligned.m8n8.trans.b16 %0, %1;" : "=r"(r) : "r"(a)); return r; }
template <bool ACC> __device__ __forceinline__ void mma16(float* d, uint32_t a0, uint32_t a1, uint32_t a2, uint32_t a3, uint32_t b0, uint32_t b1) {
  if (ACC) asm("mma.sync.aligned.m16n8k16.row.col.f32.bf16.bf16.f32 {%0,%1,%2,%3}, {%4,%5,%6,%7}, {%8,%9}, {%0,%1,%2,%3};"
               : "+f"(d[0]), "+f"(d[1]), "+f"(d[2]), "+f"(d[3]) : "r"(a0), "r"(a1), "r"(a2), "r"(a3), "r"(b0), "r"(b1));
  else asm("mma.sync.aligned.m16n8k16.row.col.f32.bf16.bf16.f32 {%0,%1,%2,%3}, {%4,%5,%6,%7}, {%8,%9}, {%10,%10,%10,%10};"
           : "=f"(d[0]), "=f"(d[1]), "=f"(d[2]), "=f"(d[3]) : "r"(a0), "r"(a1), "r"(a2), "r"(a3), "r"(b0), "r"(b1), "f"(0.f));
}
__device__ __forceinline__ uint32_t pin(uint32_t v) { uint32_t r; asm volatile("shfl.sync.bfly.b32 %0, %1, 0, 31, 0xffffffff;" : "=r"(r) : "r"(v)); return r; }
template <class T> __device__ __forceinline__ T* pin(T* p) {
  const uint64_t a = reinterpret_cast<uint64_t>(p);
  return reinterpret_cast<T*>((uint64_t)pin((uint32_t)a) | ((uint64_t)pin((uint32_t)(a >> 32)) << 32));
}
__device__ __forceinline__ uint32_t upin(uint32_t v) { return __shfl_sync(0xffffffffu, v, 0); }
template <class T> __device__ __forceinline__ T* upin(T* p) {
  const uint64_t a = reinterpret_cast<uint64_t>(p);
  return reinterpret_cast<T*>((uint64_t)upin((uint32_t)a) | ((uint64_t)upin((uint32_t)(a >> 32)) << 32));
}
__device__ __forceinline__ bool elect() {
  uint32_t p;
  asm volatile("{\n.reg .pred P;\nelect.sync _|P, 0xffffffff;\nselp.u32 %0, 1, 0, P;\n}" : "=r"(p));
  return p;
}
__device__ __forceinline__ uint32_t set_tag(uint32_t w, uint32_t tag) { uint32_t r; asm("lop3.b32 %0, %1, 0xfffffffe, %2, 0xea;" : "=r"(r) : "r"(w), "r"(tag)); return r; }
__device__ __forceinline__ uint32_t bitsel(uint32_t w, uint32_t m, uint32_t o) { uint32_t r; asm("lop3.b32 %0, %1, %2, %3, 0xe2;" : "=r"(r) : "r"(w), "r"(m), "r"(o)); return r; }
__device__ __forceinline__ uint32_t or3(uint32_t a, uint32_t b, uint32_t c) { uint32_t r; asm("lop3.b32 %0, %1, %2, %3, 0xfe;" : "=r"(r) : "r"(a), "r"(b), "r"(c)); return r; }
__device__ __forceinline__ uint32_t diff2(uint32_t a, uint32_t b, uint32_t tag) { uint32_t r; asm("lop3.b32 %0, %1, %2, %3, 0x7e;" : "=r"(r) : "r"(a), "r"(b), "r"(tag)); return r; }
__device__ __forceinline__ float2 cmul(float2 a, float2 b) { return make_float2(a.x * b.x - a.y * b.y, a.x * b.y + a.y * b.x); }

template<int TB> __device__ __forceinline__ void wgmma_ss_160_0(float (&d)[96], uint32_t al, uint32_t ah, uint32_t bl, uint32_t bh) {
  asm volatile("{\n.reg .b64 da, db;\nmov.b64 da, {%80, %81};\nmov.b64 db, {%82, %83};\n"
    "wgmma.mma_async.sync.aligned.m64n160k16.f32.bf16.bf16 {%0,%1,%2,%3,%4,%5,%6,%7,%8,%9,%10,%11,%12,%13,%14,%15,%16,%17,%18,%19,%20,%21,%22,%23,%24,%25,%26,%27,%28,%29,%30,%31,%32,%33,%34,%35,%36,%37,%38,%39,%40,%41,%42,%43,%44,%45,%46,%47,%48,%49,%50,%51,%52,%53,%54,%55,%56,%57,%58,%59,%60,%61,%62,%63,%64,%65,%66,%67,%68,%69,%70,%71,%72,%73,%74,%75,%76,%77,%78,%79}, da, db, 1, 1, 1, 1, %84;\n}\n"
    : "+f"(d[0]),"+f"(d[1]),"+f"(d[2]),"+f"(d[3]),"+f"(d[4]),"+f"(d[5]),"+f"(d[6]),"+f"(d[7]),"+f"(d[8]),"+f"(d[9]),"+f"(d[10]),"+f"(d[11]),"+f"(d[12]),"+f"(d[13]),"+f"(d[14]),"+f"(d[15]),"+f"(d[16]),"+f"(d[17]),"+f"(d[18]),"+f"(d[19]),"+f"(d[20]),"+f"(d[21]),"+f"(d[22]),"+f"(d[23]),"+f"(d[24]),"+f"(d[25]),"+f"(d[26]),"+f"(d[27]),"+f"(d[28]),"+f"(d[29]),"+f"(d[30]),"+f"(d[31]),"+f"(d[32]),"+f"(d[33]),"+f"(d[34]),"+f"(d[35]),"+f"(d[36]),"+f"(d[37]),"+f"(d[38]),"+f"(d[39]),"+f"(d[40]),"+f"(d[41]),"+f"(d[42]),"+f"(d[43]),"+f"(d[44]),"+f"(d[45]),"+f"(d[46]),"+f"(d[47]),"+f"(d[48]),"+f"(d[49]),"+f"(d[50]),"+f"(d[51]),"+f"(d[52]),"+f"(d[53]),"+f"(d[54]),"+f"(d[55]),"+f"(d[56]),"+f"(d[57]),"+f"(d[58]),"+f"(d[59]),"+f"(d[60]),"+f"(d[61]),"+f"(d[62]),"+f"(d[63]),"+f"(d[64]),"+f"(d[65]),"+f"(d[66]),"+f"(d[67]),"+f"(d[68]),"+f"(d[69]),"+f"(d[70]),"+f"(d[71]),"+f"(d[72]),"+f"(d[73]),"+f"(d[74]),"+f"(d[75]),"+f"(d[76]),"+f"(d[77]),"+f"(d[78]),"+f"(d[79])
    : "r"(al), "r"(ah), "r"(bl), "r"(bh), "n"(TB));
}
template<int TB> __device__ __forceinline__ void wgmma_ss_144_0(float (&d)[96], uint32_t al, uint32_t ah, uint32_t bl, uint32_t bh) {
  asm volatile("{\n.reg .b64 da, db;\nmov.b64 da, {%72, %73};\nmov.b64 db, {%74, %75};\n"
    "wgmma.mma_async.sync.aligned.m64n144k16.f32.bf16.bf16 {%0,%1,%2,%3,%4,%5,%6,%7,%8,%9,%10,%11,%12,%13,%14,%15,%16,%17,%18,%19,%20,%21,%22,%23,%24,%25,%26,%27,%28,%29,%30,%31,%32,%33,%34,%35,%36,%37,%38,%39,%40,%41,%42,%43,%44,%45,%46,%47,%48,%49,%50,%51,%52,%53,%54,%55,%56,%57,%58,%59,%60,%61,%62,%63,%64,%65,%66,%67,%68,%69,%70,%71}, da, db, 1, 1, 1, 1, %76;\n}\n"
    : "+f"(d[0]),"+f"(d[1]),"+f"(d[2]),"+f"(d[3]),"+f"(d[4]),"+f"(d[5]),"+f"(d[6]),"+f"(d[7]),"+f"(d[8]),"+f"(d[9]),"+f"(d[10]),"+f"(d[11]),"+f"(d[12]),"+f"(d[13]),"+f"(d[14]),"+f"(d[15]),"+f"(d[16]),"+f"(d[17]),"+f"(d[18]),"+f"(d[19]),"+f"(d[20]),"+f"(d[21]),"+f"(d[22]),"+f"(d[23]),"+f"(d[24]),"+f"(d[25]),"+f"(d[26]),"+f"(d[27]),"+f"(d[28]),"+f"(d[29]),"+f"(d[30]),"+f"(d[31]),"+f"(d[32]),"+f"(d[33]),"+f"(d[34]),"+f"(d[35]),"+f"(d[36]),"+f"(d[37]),"+f"(d[38]),"+f"(d[39]),"+f"(d[40]),"+f"(d[41]),"+f"(d[42]),"+f"(d[43]),"+f"(d[44]),"+f"(d[45]),"+f"(d[46]),"+f"(d[47]),"+f"(d[48]),"+f"(d[49]),"+f"(d[50]),"+f"(d[51]),"+f"(d[52]),"+f"(d[53]),"+f"(d[54]),"+f"(d[55]),"+f"(d[56]),"+f"(d[57]),"+f"(d[58]),"+f"(d[59]),"+f"(d[60]),"+f"(d[61]),"+f"(d[62]),"+f"(d[63]),"+f"(d[64]),"+f"(d[65]),"+f"(d[66]),"+f"(d[67]),"+f"(d[68]),"+f"(d[69]),"+f"(d[70]),"+f"(d[71])
    : "r"(al), "r"(ah), "r"(bl), "r"(bh), "n"(TB));
}
template<int TB> __device__ __forceinline__ void wgmma_ss_96_0(float (&d)[96], uint32_t al, uint32_t ah, uint32_t bl, uint32_t bh) {
  asm volatile("{\n.reg .b64 da, db;\nmov.b64 da, {%48, %49};\nmov.b64 db, {%50, %51};\n"
    "wgmma.mma_async.sync.aligned.m64n96k16.f32.bf16.bf16 {%0,%1,%2,%3,%4,%5,%6,%7,%8,%9,%10,%11,%12,%13,%14,%15,%16,%17,%18,%19,%20,%21,%22,%23,%24,%25,%26,%27,%28,%29,%30,%31,%32,%33,%34,%35,%36,%37,%38,%39,%40,%41,%42,%43,%44,%45,%46,%47}, da, db, 1, 1, 1, 1, %52;\n}\n"
    : "+f"(d[0]),"+f"(d[1]),"+f"(d[2]),"+f"(d[3]),"+f"(d[4]),"+f"(d[5]),"+f"(d[6]),"+f"(d[7]),"+f"(d[8]),"+f"(d[9]),"+f"(d[10]),"+f"(d[11]),"+f"(d[12]),"+f"(d[13]),"+f"(d[14]),"+f"(d[15]),"+f"(d[16]),"+f"(d[17]),"+f"(d[18]),"+f"(d[19]),"+f"(d[20]),"+f"(d[21]),"+f"(d[22]),"+f"(d[23]),"+f"(d[24]),"+f"(d[25]),"+f"(d[26]),"+f"(d[27]),"+f"(d[28]),"+f"(d[29]),"+f"(d[30]),"+f"(d[31]),"+f"(d[32]),"+f"(d[33]),"+f"(d[34]),"+f"(d[35]),"+f"(d[36]),"+f"(d[37]),"+f"(d[38]),"+f"(d[39]),"+f"(d[40]),"+f"(d[41]),"+f"(d[42]),"+f"(d[43]),"+f"(d[44]),"+f"(d[45]),"+f"(d[46]),"+f"(d[47])
    : "r"(al), "r"(ah), "r"(bl), "r"(bh), "n"(TB));
}
template<int TB> __device__ __forceinline__ void wgmma_ss_96_48(float (&d)[96], uint32_t al, uint32_t ah, uint32_t bl, uint32_t bh) {
  asm volatile("{\n.reg .b64 da, db;\nmov.b64 da, {%48, %49};\nmov.b64 db, {%50, %51};\n"
    "wgmma.mma_async.sync.aligned.m64n96k16.f32.bf16.bf16 {%0,%1,%2,%3,%4,%5,%6,%7,%8,%9,%10,%11,%12,%13,%14,%15,%16,%17,%18,%19,%20,%21,%22,%23,%24,%25,%26,%27,%28,%29,%30,%31,%32,%33,%34,%35,%36,%37,%38,%39,%40,%41,%42,%43,%44,%45,%46,%47}, da, db, 1, 1, 1, 1, %52;\n}\n"
    : "+f"(d[48]),"+f"(d[49]),"+f"(d[50]),"+f"(d[51]),"+f"(d[52]),"+f"(d[53]),"+f"(d[54]),"+f"(d[55]),"+f"(d[56]),"+f"(d[57]),"+f"(d[58]),"+f"(d[59]),"+f"(d[60]),"+f"(d[61]),"+f"(d[62]),"+f"(d[63]),"+f"(d[64]),"+f"(d[65]),"+f"(d[66]),"+f"(d[67]),"+f"(d[68]),"+f"(d[69]),"+f"(d[70]),"+f"(d[71]),"+f"(d[72]),"+f"(d[73]),"+f"(d[74]),"+f"(d[75]),"+f"(d[76]),"+f"(d[77]),"+f"(d[78]),"+f"(d[79]),"+f"(d[80]),"+f"(d[81]),"+f"(d[82]),"+f"(d[83]),"+f"(d[84]),"+f"(d[85]),"+f"(d[86]),"+f"(d[87]),"+f"(d[88]),"+f"(d[89]),"+f"(d[90]),"+f"(d[91]),"+f"(d[92]),"+f"(d[93]),"+f"(d[94]),"+f"(d[95])
    : "r"(al), "r"(ah), "r"(bl), "r"(bh), "n"(TB));
}
__device__ __forceinline__ void wgmma_rs_72(float (&d)[36], uint32_t a0, uint32_t a1, uint32_t a2, uint32_t a3, uint32_t bl, uint32_t bh, int sd) {
  asm volatile("{\n.reg .pred p;\n.reg .b64 db;\nsetp.ne.b32 p, %42, 0;\nmov.b64 db, {%40, %41};\n"
    "wgmma.mma_async.sync.aligned.m64n72k16.f32.bf16.bf16 {%0,%1,%2,%3,%4,%5,%6,%7,%8,%9,%10,%11,%12,%13,%14,%15,%16,%17,%18,%19,%20,%21,%22,%23,%24,%25,%26,%27,%28,%29,%30,%31,%32,%33,%34,%35}, {%36,%37,%38,%39}, db, p, 1, 1, 1;\n}\n"
    : "+f"(d[0]),"+f"(d[1]),"+f"(d[2]),"+f"(d[3]),"+f"(d[4]),"+f"(d[5]),"+f"(d[6]),"+f"(d[7]),"+f"(d[8]),"+f"(d[9]),"+f"(d[10]),"+f"(d[11]),"+f"(d[12]),"+f"(d[13]),"+f"(d[14]),"+f"(d[15]),"+f"(d[16]),"+f"(d[17]),"+f"(d[18]),"+f"(d[19]),"+f"(d[20]),"+f"(d[21]),"+f"(d[22]),"+f"(d[23]),"+f"(d[24]),"+f"(d[25]),"+f"(d[26]),"+f"(d[27]),"+f"(d[28]),"+f"(d[29]),"+f"(d[30]),"+f"(d[31]),"+f"(d[32]),"+f"(d[33]),"+f"(d[34]),"+f"(d[35])
    : "r"(a0), "r"(a1), "r"(a2), "r"(a3), "r"(bl), "r"(bh), "r"(sd));
}
__device__ __forceinline__ void wgmma_rs_48(float (&d)[24], uint32_t a0, uint32_t a1, uint32_t a2, uint32_t a3, uint32_t bl, uint32_t bh, int sd) {
  asm volatile("{\n.reg .pred p;\n.reg .b64 db;\nsetp.ne.b32 p, %30, 0;\nmov.b64 db, {%28, %29};\n"
    "wgmma.mma_async.sync.aligned.m64n48k16.f32.bf16.bf16 {%0,%1,%2,%3,%4,%5,%6,%7,%8,%9,%10,%11,%12,%13,%14,%15,%16,%17,%18,%19,%20,%21,%22,%23}, {%24,%25,%26,%27}, db, p, 1, 1, 1;\n}\n"
    : "+f"(d[0]),"+f"(d[1]),"+f"(d[2]),"+f"(d[3]),"+f"(d[4]),"+f"(d[5]),"+f"(d[6]),"+f"(d[7]),"+f"(d[8]),"+f"(d[9]),"+f"(d[10]),"+f"(d[11]),"+f"(d[12]),"+f"(d[13]),"+f"(d[14]),"+f"(d[15]),"+f"(d[16]),"+f"(d[17]),"+f"(d[18]),"+f"(d[19]),"+f"(d[20]),"+f"(d[21]),"+f"(d[22]),"+f"(d[23])
    : "r"(a0), "r"(a1), "r"(a2), "r"(a3), "r"(bl), "r"(bh), "r"(sd));
}
template<int N,int OFF,int TB> __device__ __forceinline__ void wgmma_ss(float (&d)[96], uint32_t al, uint32_t ah, uint32_t bl, uint32_t bh) {
  if constexpr (N==160 && OFF==0) wgmma_ss_160_0<TB>(d, al, ah, bl, bh);
  else if constexpr (N==144 && OFF==0) wgmma_ss_144_0<TB>(d, al, ah, bl, bh);
  else if constexpr (N==96 && OFF==0) wgmma_ss_96_0<TB>(d, al, ah, bl, bh);
  else if constexpr (N==96 && OFF==48) wgmma_ss_96_48<TB>(d, al, ah, bl, bh);
}

__device__ __forceinline__ void dft3(float2& a, float2& b, float2& c) {
  const float s = 0.86602540378443864676f;
  float2 t = make_float2(b.x + c.x, b.y + c.y), d = make_float2(b.x - c.x, b.y - c.y);
  float2 m = make_float2(fmaf(-0.5f, t.x, a.x), fmaf(-0.5f, t.y, a.y));
  a = make_float2(a.x + t.x, a.y + t.y);
  b = make_float2(fmaf(s, d.y, m.x), fmaf(-s, d.x, m.y));
  c = make_float2(fmaf(-s, d.y, m.x), fmaf(s, d.x, m.y));
}
__device__ __forceinline__ void dft9(float2 (&x)[9]) {
  const float2 w1 = make_float2(0.76604444311897803520f, -0.64278760968653932632f);
  const float2 w2 = make_float2(0.17364817766693034885f, -0.98480775301220805937f);
  const float2 w4 = make_float2(-0.93969262078590838405f, -0.34202014332566873304f);
  dft3(x[0], x[3], x[6]); dft3(x[1], x[4], x[7]); dft3(x[2], x[5], x[8]);
  x[4] = cmul(x[4], w1); x[7] = cmul(x[7], w2); x[5] = cmul(x[5], w2); x[8] = cmul(x[8], w4);
  dft3(x[0], x[1], x[2]); dft3(x[3], x[4], x[5]); dft3(x[6], x[7], x[8]);
  float2 t;
  t = x[1]; x[1] = x[3]; x[3] = t;
  t = x[2]; x[2] = x[6]; x[6] = t;
  t = x[5]; x[5] = x[7]; x[7] = t;
}

__device__ __forceinline__ uint32_t* mod_ptr(Scratch* sc, int u, int t128) {
  const int i = t128 & 15;
  return u < 72 ? sc->moda + (t128 >> 4) * (2 * D_) + 16 * u + 2 * (i & 7) + (i >> 3) : sc->mod + 16 * (u - 72) + i;
}
__device__ __forceinline__ void mod_unit(Scratch* sc, int u, int t128, uint32_t sw_, uint32_t bar, int ph, uint32_t rb, uint32_t tag) {
  const int w = t128 >> 5, l = t128 & 31;
  uint32_t b[18];
#pragma unroll
  for (int i = 0; i < 18; i++) b[i] = lds(red + 512 + (72 * w + 4 * i + (l & 3)) * 4);
  const uint32_t sa = pin(sw_ + (144 * w + (l & 7) + 8 * (l >> 4)) * 32 + (((l >> 3) ^ (l >> 2)) & 1) * 16);
  const uint32_t sr = pin(rb + (l >> 2) * 16 + w * 4);
  uint32_t* const dst = pin(mod_ptr(sc, u, t128));
  const int kind = u / 36;
  const float mul = __uint_as_float(pin(__float_as_uint(kind == 0 ? 16.0f : 1.0f))), add = __uint_as_float(pin(__float_as_uint(kind == 1 || kind == 4 ? 1.0f : 0.0f)));
  mbar_wait(bar, ph);
  if (t128 == 0 && u < 72) TS(10);
  float d[3][4];
#pragma unroll
  for (int i = 0; i < 9; i++) {
    uint32_t a0, a1, a2, a3;
    asm volatile("ldmatrix.sync.aligned.m8n8.x4.trans.shared.b16 {%0,%1,%2,%3}, [%4];" : "=r"(a0), "=r"(a1), "=r"(a2), "=r"(a3) : "r"(sa + i * 512) : "memory");
    if (i < 3) mma16<false>(d[i], a0, a1, a2, a3, b[2 * i], b[2 * i + 1]);
    else mma16<true>(d[i % 3], a0, a1, a2, a3, b[2 * i], b[2 * i + 1]);
  }
  if ((l & 3) == 0) { sts(sr, __float_as_uint(d[0][0] + d[1][0] + d[2][0])); sts(sr + 128, __float_as_uint(d[0][2] + d[1][2] + d[2][2])); }
  bar_sync(4, 128);
  const uint4 v = lds4(rb + (l & 15) * 16);
  const float m = rbf(fmaf(rbf((__uint_as_float(v.x) + __uint_as_float(v.y)) + (__uint_as_float(v.z) + __uint_as_float(v.w))), mul, add));
  if (u < 72 || t128 < 16) *dst = __float_as_uint(m) | tag;
}

__device__ __forceinline__ float rsq(float x) { float r; asm("rsqrt.approx.ftz.f32 %0, %1;" : "=f"(r) : "f"(x)); return r; }
__device__ __forceinline__ void ln_stats2(const float (&a)[18], const float (&b)[18], float sc, float& oa, float& ra, float& ob, float& rb) {
  float v[4] = {0.f, 0.f, 0.f, 0.f}, w[4] = {0.f, 0.f, 0.f, 0.f};
#pragma unroll
  for (int i = 0; i < 18; i += 2) {
    v[0] += a[i]; v[1] = fmaf(a[i], a[i], v[1]); v[2] += b[i]; v[3] = fmaf(b[i], b[i], v[3]);
    w[0] += a[i + 1]; w[1] = fmaf(a[i + 1], a[i + 1], w[1]); w[2] += b[i + 1]; w[3] = fmaf(b[i + 1], b[i + 1], w[3]);
  }
#pragma unroll
  for (int e = 0; e < 4; e++) v[e] += w[e];
#pragma unroll
  for (int o = 16; o; o >>= 1) {
#pragma unroll
    for (int e = 0; e < 4; e++) v[e] += __shfl_xor_sync(0xffffffffu, v[e], o);
  }
  const float ma = v[0] * (1.0f / D_), mb = v[2] * (1.0f / D_);
  ra = sc * rsq(fmaxf(fmaf(-ma, ma, v[1] * (1.0f / D_)), 0.f) + 1e-5f);
  rb = sc * rsq(fmaxf(fmaf(-mb, mb, v[3] * (1.0f / D_)), 0.f) + 1e-5f);
  oa = -ma * ra; ob = -mb * rb;
}

__device__ __forceinline__ void ln_stats1(const float (&a)[18], float sc, float& oa, float& ra) {
  float v[3] = {a[0], a[1], a[2]}, w[3] = {a[0] * a[0], a[1] * a[1], a[2] * a[2]};
#pragma unroll
  for (int i = 3; i < 18; i++) { v[i % 3] += a[i]; w[i % 3] = fmaf(a[i], a[i], w[i % 3]); }
  float s = v[0] + v[1] + v[2], q = w[0] + w[1] + w[2];
#pragma unroll
  for (int o = 16; o; o >>= 1) { s += __shfl_xor_sync(0xffffffffu, s, o); q += __shfl_xor_sync(0xffffffffu, q, o); }
  const float m = s * (1.0f / D_);
  ra = sc * rsq(fmaxf(fmaf(-m, m, q * (1.0f / D_)), 0.f) + 1e-5f);
  oa = -m * ra;
}

__device__ __forceinline__ float tmat(int c, int q, int j) {
  const int ph = q == 1 ? 1024 * j : (q >> 1) * (c + 128 * j) + 512 * (q & 1);
  return __cosf((float)(((ph + 1024) & 2047) - 1024) * (6.283185307179586f / 2048.0f));
}
__device__ __forceinline__ uint32_t line_off(int k1, int kap, int pi, int f) {
  int kd = 64 * k1 + 9 * kap;
  if (kap == 0 && k1 > 4) kd -= 288;
  if (kd >= D_) kd -= D_;
  return pi * 2400 + ((min(kd, D_ - kd) ^ f) << 3);
}

constexpr int JSK = 5;
struct Ring { uint32_t st, ph; };
template <bool G2, class T> __device__ __forceinline__ void ring_next(T& st, T& ph) {
  if (++st == NST) st = 0;
  ph ^= ((G2 ? 0xDu : 0x1u) >> st) & 1;
}
__device__ __forceinline__ void arrive_if(uint32_t a, uint32_t p) {
  asm volatile("{\n.reg .pred p;\nsetp.ne.u32 p, %1, 0;\n@p mbarrier.arrive.shared::cta.b64 _, [%0];\n}" ::"r"(a), "r"(p) : "memory");
}
template <int NA> __device__ __forceinline__ void reg_fence_n(float (&d)[96]) {
#pragma unroll
  for (int i = 0; i < NA; i++) asm volatile("" : "+f"(d[i])::"memory");
}
template <int MODE>
__device__ __forceinline__ void gemm_main(float (&acc)[96], uint32_t da0, uint32_t da1, uint32_t db0, int wg, Ring& rg,
                                          bool rows, uint32_t* x1p, const uint32_t (&xr)[18]) {
  static_assert(JSK == NST - 1, "the held slot is the first one that is not refilled by GEMM1");
  constexpr int NKB = MODE == 3 ? 36 : 32, J = MODE == 3 ? J2 : JSK;
  constexpr uint32_t HA = 0x40000040u, HB = MODE == 3 ? 0x40000040u : 0x80000020u;
  constexpr uint32_t KA = 2048 >> 4, KB = MODE == 3 ? (32 >> 4) : (1024 >> 4);
  constexpr int NA = MODE == 3 ? 72 : MODE == 1 ? 96 : 80;
  const uint32_t t = threadIdx.x & 127;
  const uint32_t eb = full0 + 8 * NST;
  uint32_t pb = 0, rel = t == 0, prel = 0, ok = 0;
  int n = MODE == 3 ? NKB - J : X1K + 2 * wg;
#pragma unroll 1
  for (int pass = MODE == 3 ? 0 : -1;; pass++) {
#pragma unroll 1
    do {
      const uint32_t so = rg.st * ((MODE == 3 ? STAGE2 : STAGE) >> 4), cb = eb + 8 * rg.st;
      if (__builtin_expect(!ok, 0)) mbar_wait(full0 + 8 * rg.st, rg.ph);
      reg_fence_n<NA>(acc);
      if (MODE == 1 && wg) {
        wg_fence();
#pragma unroll
        for (int k = 0; k < 4; k++) wgmma_ss<96, 48, 1>(acc, da1 + so + k * KA, HA, db0 + so + k * KB, HB);
        wg_commit();
      }
      wg_fence();
#pragma unroll
      for (int k = 0; k < 4; k++) {
        if (k == 3) { ring_next<MODE == 3>(rg.st, rg.ph); ok = PEEK ? mbar_test(full0 + 8 * rg.st, rg.ph) : 0; }
        if (MODE == 0) wgmma_ss<160, 0, 1>(acc, da0 + so + k * KA, HA, db0 + so + k * KB, HB);
        else if (MODE == 3) wgmma_ss<144, 0, 0>(acc, da0 + so + k * KA, HA, db0 + so + k * KB, HB);
        else wgmma_ss<96, 0, 1>(acc, da0 + so + k * KA, HA, db0 + so + k * KB, HB);
      }
      wg_commit();
      wg_wait<1>();
      reg_fence_n<NA>(acc);
      arrive_if(pb, prel);
      pb = cb; prel = rel;
    } while (--n);
    if (pass == 2 - wg) break;
    if (MODE != 3 && pass < 0) {
      if (rows) {
#pragma unroll
        for (int i = 0; i < 9; i++) { x1p[32 * i] = xr[i]; x1p[512 * 288 + 32 * i] = xr[9 + i]; }
      }
      n = NKB - JSK - X1K - 2 * wg;
      continue;
    }
    n = 1;
    if (pass == 0) {
      if (MODE != 3) prel = rel & wg;
      else { rel = 0; if (J < NST) prel = 0; }
      n = J - 1 + wg;
      if (!wg) continue;
      wg_wait<0>();
      arrive_if(pb, prel);
      prel = 0;
    }
    bar_sync(1, 256);
  }
  wg_wait<0>();
  reg_fence_n<NA>(acc);
  if (MODE != 3) arrive_if(pb, MODE == 1 ? prel & ~wg : prel);
}

constexpr float GK1 = 2.0f * 0.7978845608028654f, GK3 = 8.0f * 0.044715f * 0.7978845608028654f;

__device__ __forceinline__ int kb2_order(int i) { const int wv = i / 6; return 6 * (i - 6 * wv) + ((0x431250 >> (4 * wv)) & 7); }

__device__ __forceinline__ int kb2_pos(int kb) { const int hf = kb >= 36, k = kb - 36 * hf, gr = k / 6; return 64 * hf + gr + 6 * ((0x154230 >> (4 * (k - 6 * gr))) & 7); }

__device__ __forceinline__ void wait_flags(const unsigned* p, int idx, unsigned target, uint32_t& ready) {
  int it = 0;
  while (!((ready >> idx) & 1) && it++ < SPIN_MAX) ready = __ballot_sync(0xffffffffu, (int)(ld_rlx(p) - target) >= 0);
}

enum { B_FULL = 0, B_EMPTY = 6, B_S4 = 12, B_S5, B_LAND, B_FLT = B_LAND + 6, B_Z1, B_Z2, B_GO, B_X, B_WM, B_NUM, B_W0 = B_NUM };

__global__ void __launch_bounds__(NTHR, 1)
fused_kernel(const Params p, const __grid_constant__ Maps maps) {
  extern __shared__ __align__(1024) uint8_t smem_raw[];
  const int bx = blockIdx.x, cta = bx < 112 || bx >= 130 ? bx : bx < 114 ? bx + 16 : bx - 2;
  const int tid = threadIdx.x, t128 = tid & 127;
  const int wp = __shfl_sync(0xffffffffu, tid >> 5, 0), wg = wp >> 2;
  const int l = tid & 31, g = l >> 2, t = l & 3;
  Scratch* const sc = p.s;
  const bool rows = cta < 128;
  const int mu = rows ? cta + 4 : cta - 128;
  const int R = mu - 12;

  uint32_t xr[18];
  uint32_t cv[3];
  const unsigned ep0 = ld_rlx(&sc->cnt[C_EP + l]);
  if (tid == 0) TS(0);
  if (wg == 2) {
#pragma unroll
    for (int i = 0; i < 3; i++) cv[i] = ld_nc(reinterpret_cast<const uint32_t*>(p.c) + min(t128 + 128 * i, 287));
    if (wp == 9 && l < 9 && rows) {
      const int h = 9 * cta + l;
      prefetch_l2(reinterpret_cast<const uint8_t*>(p.wmod) + (size_t)(h >> 1) * (12 * D_) + (h & 1) * (2 * D_), 2 * D_);
    }
    if (tid == 256 && mu < 72) {
      mbar_init(full0 + 8 * B_W0, 1);
      fence_async_smem();
      mbar_expect(full0 + 8 * B_W0, 18432);
#pragma unroll 1
      for (int i = 0; i < 3; i++) tma2d(sbase + O_P2 + i * 6144, &maps.wm, 16 * mu, 192 * i, full0 + 8 * B_W0);
    }
    __syncwarp();
#pragma unroll 1
    for (int u = mu < 72 ? mu : 72 + mu; u < 216; u += u < 72 ? 72 : NCTA) if (u < 72 || t128 < 16) *mod_ptr(sc, u, t128) = 0;
    if (wp == 11 && smem_u32(smem_raw) != sbase) __trap();
    if (wp >= 10 && elect()) {
#pragma unroll 1
      for (int i = wp - 10; i < B_NUM; i += 2) mbar_init(full0 + 8 * i, i == B_FLT ? 4 : i == B_WM ? 3 : i < B_LAND && i != B_S4 ? 2 : 1);
      fence_async_smem();
    }
    __syncwarp();
  } else if (rows) {
    const uint32_t* xs = reinterpret_cast<const uint32_t*>(p.x) + (size_t)(cta + 128 * ((wp & 3) + 8 * wg)) * 288 + l;
#pragma unroll
    for (int i = 0; i < 9; i++) { xr[i] = ld_nc(xs + 32 * i); xr[9 + i] = ld_nc(xs + 512 * 288 + 32 * i); }
  }
  CK(0);
  if (tid == 64 && cta == NCTA - 1) prefetch_l2(p.tab, sizeof(T_TAB));
  __syncwarp();
  auto tag_of = [](unsigned e) { return (e & 0x7fffu) | 0x8000u; };
  const int kap = 8 * ((wp & 3) ^ (wg & 1)) + g;
  uint32_t tb[4], sb1[3], lo[9];
#pragma unroll
  for (int i = 0; i < 4; i++) tb[i] = pin(pack_bf16(tmat(cta, 8 * (i >> 1) + g, t + 8 * (i & 1)), tmat(cta, 8 * (i >> 1) + g, t + 8 * (i & 1) + 4)));
#pragma unroll
  for (int i = 0; i < 3; i++) {
    const int d = 48 * wp + 16 * i + (l & 15);
    sb1[i] = pin(sbase + O_B1 + (l >> 4) * 9216 + (d % 9) * 1024 + (d & 63) * 16);
  }
#pragma unroll
  for (int k1 = 0; k1 < 9; k1++) lo[k1] = pin(sbase + O_Z1 + line_off(k1, kap, 4 * wg + t, cta & 3));
  const uint32_t snt = pin(sbase + O_NRM + ((l & 7) + 8 * (l >> 4)) * 1168 + (48 * wp + (l & 8)) * 2), sn = pin(sbase + O_NRM + wp * 2336 + l * 4);
  const uint32_t smask = pin(t ? 0u : 0xffff0000u);
  const uint32_t* const mp = pin(sc->moda + (cta >> 4) * (2 * D_) + 48 * wp + 2 * g);
  const uint4* const ftab = pin(p.tab + TB_F + (t128 ^ (wg << 5)));

  if (wg == 2) {
#pragma unroll
    for (int i = 0; i < 3; i++) {
      const float c0 = bf_lo(cv[i]), c1 = bf_hi(cv[i]);
      sts(red + 512 + min(t128 + 128 * i, 287) * 4, pack_bf16(__fdividef(c0, 1.0f + __expf(-c0)), __fdividef(c1, 1.0f + __expf(-c1))));
    }
    if (t128 == 0) sts(full0 + 248, ep0 + 1);
    if (wp == 9 && l < 11) asm volatile("prefetch.tensormap [%0];" ::"l"(&maps.z1 + l) : "memory");
    bar_sync(4, 128);
    if (mu < 72) {
      mod_unit(sc, mu, t128, sbase + O_P2, full0 + 8 * B_W0, 0, red, tag_of(upin(ep0) + 1));
      if (t128 == 0) TS(25);
    }
    CK(1);
  }
  const int pi = R / 15, col0 = 20 * (R - 15 * pi);
  const int xu = DF_ * pi + col0, xv = DF_ * (pi ? 16 - pi : 8) + col0;
  auto load_filter = [&](int a) {
    const int x = (a & 1) ? xv : xu;
    const bool wide = (x & 15) > 12;
    mbar_expect(full0 + 8 * B_FLT, wide ? 12288 : 8192);
    tma2d(sbase + O_RAW + a * 12288, &maps.wf[a & 2], x & ~15, 0, full0 + 8 * B_FLT);
    if (wide) tma2d(sbase + O_RAW + a * 12288 + 8192, &maps.wf[(a & 2) + 1], (x & ~15) + 32, 0, full0 + 8 * B_FLT);
  };
  uint4 af[4];
  if (rows) {
    uint2 ms[3], mc[3];
    auto load_mod = [&](uint32_t o = 0) {
#pragma unroll
      for (int i = 0; i < 3; i++) { ms[i] = ld_rlx2(mp + 2 * o + 16 * i); mc[i] = ld_rlx2(mp + 2 * o + D_ + 16 * i); }
    };
    if (wg < 2) {
      float a[18], b[18];
#pragma unroll
      for (int i = 0; i < 9; i++) { a[2 * i] = bf_lo(xr[i]); a[2 * i + 1] = bf_hi(xr[i]); b[2 * i] = bf_lo(xr[9 + i]); b[2 * i + 1] = bf_hi(xr[9 + i]); }
      float oa, ra, ob, rb;
      ln_stats2(a, b, 1.0f, oa, ra, ob, rb);
      CK(1);
      load_mod((__float_as_uint(ra) | __float_as_uint(rb)) >> 31);
#pragma unroll
      for (int i = 0; i < 9; i++) {
        sts(sn + i * 128, pack_bf16(fmaf(a[2 * i], ra, oa), fmaf(a[2 * i + 1], ra, oa)));
        sts(sn + 1168 + i * 128, pack_bf16(fmaf(b[2 * i], rb, ob), fmaf(b[2 * i + 1], rb, ob)));
      }
      CK(2);
      bar_arrive(10, NTHR);
#pragma unroll
      for (int kk = 0; kk < 4; kk++) af[kk] = ld_nc4(ftab + kk * 128);
      bar_sync(1, 256);
      if (tid == 0) TS(2);
    } else {
      bar_sync(10, NTHR);
      load_mod();
      CK(2);
      if (wp >= 10 && elect()) prefetch_l2(reinterpret_cast<const uint8_t*>(wp == 10 ? p.wr : p.wi) + cta * 9248, 9248);
      __syncwarp();
    }
    float rs[3][8];
#pragma unroll
    for (int i = 0; i < 3; i++) {
      uint32_t a0, a1, a2, a3;
      asm volatile("ldmatrix.sync.aligned.m8n8.x4.trans.shared.b16 {%0,%1,%2,%3}, [%4];" : "=r"(a0), "=r"(a1), "=r"(a2), "=r"(a3)
                   : "r"(snt + 32 * i) : "memory");
      mma16<false>(&rs[i][0], a0, a1, a2, a3, tb[0], tb[1]);
      mma16<false>(&rs[i][4], a0, a1, a2, a3, tb[2], tb[3]);
    }
    CK(3);
    const uint32_t tag16 = tag_of(upin(ep0) + 1), tag1 = tag16 & 1;
    {
      int it = 0;
#pragma unroll 1
      while (true) {
        uint32_t bad = 0;
#pragma unroll
        for (int i = 0; i < 3; i++) bad |= diff2(ms[i].x, ms[i].y, tag16) | diff2(mc[i].x, mc[i].y, tag16);
        if (!any(bad & 0xffffu) || ++it > SPIN_MAX) break;
        load_mod();
      }
      CK(4);
      if (tid == 0) TS(3);
#pragma unroll
      for (int i = 0; i < 3; i++) {
        const float c0 = bf_hi(mc[i].x), c1 = bf_hi(mc[i].y);
        const float s0 = __uint_as_float(ms[i].x & smask), s1 = __uint_as_float(ms[i].y & smask);
        stmatrix4(sb1[i], pack_bf16(fmaf(rs[i][0], c0, s0), rs[i][1] * c0), pack_bf16(fmaf(rs[i][2], c1, s1), rs[i][3] * c1),
                  pack_bf16(rs[i][4] * c0, rs[i][5] * c0), pack_bf16(rs[i][6] * c1, rs[i][7] * c1));
      }
    }
    fence_async_smem();
    CK(5);
    if (wg == 2) {
      bar_arrive(5, NTHR);
      if (R >= 0 && elect()) load_filter(wp - 8);
      __syncwarp();
      const int slot = 4 * (cta & 7) + ((cta >> 4) & 3) + 32 * (2 * (cta >> 6) + ((cta >> 3) & 1));
      const uint32_t c0 = upin(40 * slot), c1 = upin(60 * (wp & 1)), src = upin(sbase + O_Z1 + (wp & 1) * 9600);
      const CUtensorMap* mz = upin(&maps.z1);
      unsigned* hint = pin(sc->cnt + C_Z1 + 32 * (wp & 1));
      if (wp < 10) {
        bar_sync(2 + (wp & 1), 160);
        if (elect()) tma_st2d(mz, src, c0, c1);
        pause(HD1);
        if (elect()) red_add(hint, 1);
        bulk_commit_wait();
        if (tid == 256) TS(4);
        __syncwarp();
      }
    } else {
      bar_sync(5, NTHR);
      CK(6);
      float acc[36];
      const uint32_t db = (((sbase + O_B1 + wg * 9216) & 0x3FFFF) >> 4) | ((128 >> 4) << 16);
      wg_fence();
#pragma unroll
      for (int kk = 0; kk < 4; kk++) wgmma_rs_72(acc, af[kk].x, af[kk].y, af[kk].z, af[kk].w, db + kk * 16, 1024 >> 4, kk);
      wg_commit();
      wg_wait<0>();
      reg_fence(acc);
      CK(7);
      float2 za[9], zb[9];
#pragma unroll
      for (int i = 0; i < 9; i++) { za[i] = make_float2(acc[4 * i], acc[4 * i + 2]); zb[i] = make_float2(acc[4 * i + 1], acc[4 * i + 3]); }
      dft9(za); dft9(zb);
      if ((wp & 3) == wg) {
        const float sp = g ? 0.f : 1.f;
#pragma unroll
        for (int k = 1; k < 5; k++) {
          float2 a = za[k], b = za[9 - k];
          za[k] = make_float2(fmaf(sp, b.x, a.x), fmaf(-sp, b.y, a.y)); za[9 - k] = make_float2(fmaf(-sp, a.x, b.x), fmaf(sp, a.y, b.y));
          a = zb[k]; b = zb[9 - k];
          zb[k] = make_float2(fmaf(sp, b.x, a.x), fmaf(-sp, b.y, a.y)); zb[9 - k] = make_float2(fmaf(-sp, a.x, b.x), fmaf(sp, a.y, b.y));
        }
        const uint32_t w0 = set_tag(pack_bf16(za[0].y, 0.f), tag1), w1 = pack_bf16(zb[0].y, 0.f);
        asm volatile("{\n.reg .pred p;\nsetp.eq.u32 p, %3, 0;\n@p st.shared.v2.b32 [%0], {%1,%2};\n}" ::"r"(lo[0] + 288 * 8), "r"(w0), "r"(w1), "r"(g) : "memory");
        za[0].y = g ? za[0].y : 0.f; zb[0].y = g ? zb[0].y : 0.f;
      }
#pragma unroll
      for (int k1 = 0; k1 < 9; k1++) sts2(lo[k1], set_tag(pack_bf16(za[k1].x, za[k1].y), tag1), pack_bf16(zb[k1].x, zb[k1].y));
      fence_async_smem();
      CK(8);
      bar_arrive(2 + wg, 160);
      {
        const uint32_t fx = (((cta >> 4) ^ cta) & 3) << 3, dl = O_IN - O_Z1, st = sbase + O_ST + 15360 + tid * 16;
        sts4(st, (lo[0] ^ fx) + dl, (lo[1] ^ fx) + dl, (lo[2] ^ fx) + dl, (lo[3] ^ fx) + dl);
        sts4(st + 4096, (lo[4] ^ fx) + dl, (lo[5] ^ fx) + dl, (lo[6] ^ fx) + dl, (lo[7] ^ fx) + dl);
        sts4(st + 8192, (lo[8] ^ fx) + dl, (lo[0] ^ fx) + dl + (kap ? 0 : 288 * 8),
             sbase + O_B3 + wg * 1024 + (l >> 4) * 2048 + (2 * (kap & 24) + (l & 15)) * 16, 0);
      }
    }
    {
      uint32_t sy[6];
#pragma unroll
      for (int i = 0; i < 6; i++) {
        const int rr = 16 * (wp & 3) + g + 8 * (i & 1);
        sy[i] = sbase + O_Y + (t * 584 + 64 * ((3 * wg + (i >> 1) + 63 - rr) % 9) + rr) * 4;
      }
      sts4(sbase + O_ST + tid * 16, movm(tb[0]), movm(tb[2]), movm(tb[1]), movm(tb[3]));
      sts4(sbase + O_ST + 6144 + tid * 16, sy[0], sy[1], sy[2], sy[3]);
      sts2(sbase + O_ST + 12288 + tid * 8, sy[4], sy[5]);
    }
  } else {
    __syncthreads();
  }

  const unsigned ep = upin(lds(full0 + 248));
  const uint32_t tag16 = tag_of(ep), tag1 = ep & 1;
  auto load_wm = [&](int u) {
    if (wp > 8 && elect()) {
      mbar_expect(full0 + 8 * B_WM, 6144);
      tma2d(sbase + O_NRM + (wp - 9) * 6144, &maps.wm, 16 * u, 192 * (wp - 9), full0 + 8 * B_WM);
    }
    __syncwarp();
  };
  if (R >= 0) {
    const int nl = (col0 + wp < DF_) + (wg < 2 && col0 + wp + 12 < DF_);
    uint4 cf[2][4], G[4];
#pragma unroll
    for (int i = 0; i < 4; i++) {
      cf[0][i] = __ldg(p.tab + TB_P2 + i * 32 + l);
      cf[1][i] = __ldg(p.tab + TB_P2 + (pi ? i : 4 + i) * 32 + l);
      G[i] = __ldg(p.tab + TB_P2 + (8 + i) * 32 + l);
    }
    const uint32_t* zin = sc->z1 + (size_t)R * 5120;
    if (wp == 10) {
      const uint32_t* zu = upin(zin);
      if (elect()) mbar_expect(full0 + 8 * B_Z1, 20480);
      wait_cnt(sc->cnt + C_Z1 + 32 * (pi >> 2), 128 * ep - 40 * STRESS);
      if (elect()) {
        bulk_ld(sbase + O_P2, zu, 20480, full0 + 8 * B_Z1);
        TS(12);
      }
      __syncwarp();
    }
    mbar_wait(full0 + 8 * B_FLT, 0);
    CK(9);
    float wn[16], wc[16];
#pragma unroll 1
    for (int ln = nl - 1; ln >= 0; ln--) {
      const int col = col0 + wp + 12 * ln, k2 = (57 * col) & 63;
      const bool cj = k2 > 32;
      const float nr = ((col & 31) == 0 && col != 0 && col != 288 ? 0.5f : 1.0f) / ((float)S_ * D_), ni = cj ? -nr : nr;
#pragma unroll
      for (int i = 0; i < 16; i++) wn[i] = wc[i];
#pragma unroll
      for (int cl = 0; cl < 2; cl++) {
        const int v = cl ^ (cj && pi), e = ((v ? xv : xu) & 15) + wp + 12 * ln, sh = e < 32 ? 6 : 5;
        const uint32_t base = sbase + O_RAW + v * 12288 + (e < 32 ? 2 * e : 8192 - 64 + 2 * e), msk = e < 32 ? 0x30 : 0x10;
        const int dm = v ? (cj || pi ? -1 : 0) : 0;
#pragma unroll
        for (int tt = 0; tt < 4; tt++) {
          const int kc = g + 64 * (tt >> 1) + 16 * t + 8 * (tt & 1);
          uint32_t a = base + ((((cj ? -kc : kc) + dm) & 127) << sh);
          a ^= (a >> 3) & msk;
          wc[4 * tt + 2 * cl] = lds_bf(a) * nr; wc[4 * tt + 2 * cl + 1] = lds_bf(a + 24576) * ni;
        }
      }
    }
    const float al = __uint_as_float(pin((pi ? 0x3f800000u : 0u) + (l >> 5)));
    const uint32_t tagv = pin(tag1 + (l >> 5));
    CK(10);
    uint32_t off = pin(l * 160 + ((wp ^ (g & 3)) << 3));
    uint32_t offo = pin(sbase + O_P2 + 20480 + off - 64 * l), po = 3072;
    unsigned* hz2 = pin(sc->cnt + C_Z2);
    const uint32_t do2 = pin(12288 - 32 * l);
    const CUtensorMap* mz2 = upin(&maps.z2[wp == 0]);
    const uint32_t sz2 = upin(sbase + O_P2 + 20480 + (wp ? 0 : 12288)), cz2 = upin(40 * R + (wp ? 0 : 24));
    mbar_wait(full0 + 8 * B_Z1, 0);
    CK(11);
    if (tid == 0) TS(8);
    if (wg == 2) load_wm(72 + mu);
    uint2 v[4], v2[4];
    const uint32_t o2 = nl > 1 ? 96 : 0;
#pragma unroll
    for (int i = 0; i < 4; i++) { v[i] = lds2(sbase + O_P2 + off + i * 5120); v2[i] = lds2(sbase + O_P2 + off + o2 + i * 5120); }
    auto bad2 = [&]() {
      return any(or3(or3(diff2(v[0].x, v[1].x, tagv), diff2(v[2].x, v[3].x, tagv), diff2(v2[0].x, v2[1].x, tagv)), diff2(v2[2].x, v2[3].x, tagv), 0) & 1);
    };
    if (__builtin_expect(bad2() && nl, 0)) {
      FAILCNT(0);
      int it = 0;
      do {
#pragma unroll
        for (int i = 0; i < 4; i++) {
          v[i] = ld_rlx2(reinterpret_cast<const uint8_t*>(zin) + off + i * 5120);
          v2[i] = ld_rlx2(reinterpret_cast<const uint8_t*>(zin) + off + o2 + i * 5120);
        }
      } while (bad2() && ++it < SPIN_MAX);
    }
#pragma unroll 1
    for (int ln = 0; ln < nl; ln++, offo += do2, po = 2048) {
      float d[4][4];
      uint32_t A[8];
#pragma unroll
      for (int h = 0; h < 2; h++) {
        mma16<false>(d[2 * h], cf[0][0].x, cf[0][0].y, cf[0][0].z, cf[0][0].w, v[h].x, v[2 + h].x);
        mma16<false>(d[2 * h + 1], cf[1][0].x, cf[1][0].y, cf[1][0].z, cf[1][0].w, v[h].y, v[2 + h].y);
      }
      if (ln) { fence_async_smem(); bar_arrive(15, NTHR); }
#pragma unroll
      for (int h = 0; h < 2; h++)
#pragma unroll
        for (int L = 0; L < 2; L++) {
          const uint4 tw = cf[L][2 + h];
          const float* z = d[2 * h + L];
          const float2 z0 = cmul(make_float2(z[0], z[2]), make_float2(__uint_as_float(tw.x), __uint_as_float(tw.y)));
          const float2 z1 = cmul(make_float2(z[1], z[3]), make_float2(__uint_as_float(tw.z), __uint_as_float(tw.w)));
          A[4 * h + L] = pack_bf16(z0.x, z0.y); A[4 * h + 2 + L] = pack_bf16(z1.x, z1.y);
        }
#pragma unroll
      for (int tt = 0; tt < 4; tt++) {
        mma16<false>(d[tt], A[0], A[1], A[2], A[3], G[tt].x, G[tt].y);
        mma16<true>(d[tt], A[4], A[5], A[6], A[7], G[tt].z, G[tt].w);
      }
#pragma unroll
      for (int tt = 0; tt < 4; tt++) {
        const float ar = d[tt][0], aj = d[tt][1], br = d[tt][2], bj = d[tt][3];
        const float2 y1 = cmul(make_float2(fmaf(-al, bj, ar), fmaf(al, br, aj)), make_float2(wc[4 * tt], wc[4 * tt + 1]));
        const float2 y2 = cmul(make_float2(fmaf(al, ar, bj), fmaf(al, aj, -br)), make_float2(wc[4 * tt + 2], wc[4 * tt + 3]));
        A[2 * tt] = pack_bf16(fmaf(al, y2.x, y1.x), fmaf(-al, y2.y, -y1.y));
        A[2 * tt + 1] = pack_bf16(fmaf(al, y1.y, -y2.y), fmaf(al, y1.x, -y2.x));
      }
#pragma unroll
      for (int i = 0; i < 16; i++) wc[i] = wn[i];
#pragma unroll
      for (int i = 0; i < 4; i++) v[i] = v2[i];
#pragma unroll
      for (int tt = 0; tt < 4; tt++) {
        mma16<false>(d[tt], A[0], A[1], A[2], A[3], G[tt].x, G[tt].y);
        mma16<true>(d[tt], A[4], A[5], A[6], A[7], G[tt].z, G[tt].w);
      }
#pragma unroll
      for (int h = 0; h < 2; h++)
#pragma unroll
        for (int L = 0; L < 2; L++) {
          const uint4 tw = cf[L][2 + h];
          const float2 z0 = cmul(make_float2(d[2 * h][2 * L], d[2 * h][2 * L + 1]), make_float2(__uint_as_float(tw.x), __uint_as_float(tw.y)));
          const float2 z1 = cmul(make_float2(d[2 * h + 1][2 * L], d[2 * h + 1][2 * L + 1]), make_float2(__uint_as_float(tw.z), __uint_as_float(tw.w)));
          A[4 * h + 2 * L] = movm(pack_bf16(z0.x, z1.x)); A[4 * h + 2 * L + 1] = movm(pack_bf16(z0.y, z1.y));
        }
#pragma unroll
      for (int h = 0; h < 2; h++) {
        mma16<false>(d[0], cf[0][1].x, cf[0][1].y, cf[0][1].z, cf[0][1].w, A[4 * h], A[4 * h + 1]);
        mma16<false>(d[1], cf[1][1].x, cf[1][1].y, cf[1][1].z, cf[1][1].w, A[4 * h + 2], A[4 * h + 3]);
#pragma unroll
        for (int e = 0; e < 2; e++)
          sts2(offo + (2 * h + e) * po, set_tag(pack_bf16(d[0][e], d[0][2 + e]), tagv), pack_bf16(d[1][e], d[1][2 + e]));
      }
      CK(12 + ln);
    }
    if (tid == 0) TS(1);
    fence_async_smem();
    if (nl < 2 && wp != 8) bar_arrive(15, NTHR);
    if (wp) bar_arrive(6, NTHR);
    if (!(wp & 7)) {
      bar_sync(wp ? 15 : 6, NTHR);
      if (elect()) tma_st2d(mz2, sz2, cz2, 0);
      if (wp == 0 && elect()) red_add(hz2, 1);
      if (tid == 0) TS(9);
      if (wp == 0) bulk_commit_wait();
      __syncwarp();
    }
  }
  if (wg == 2) {
#pragma unroll 1
    for (int u = 72 + mu, k = 0; u < 216; u += NCTA, k ^= 1) {
      if (R < 0) { fence_async_smem(); bar_sync(4, 128); load_wm(u); }
      mod_unit(sc, u, t128, sbase + O_NRM, full0 + 8 * B_WM, k, red + 256 - 256 * k, tag16);
    }
    fence_async_smem();
    CK(13);
  }

  const int grp = bx / 11, m1 = bx - 11 * grp;
  const bool helper = (m1 & 3) == 3;
  const int f1 = 384 * grp + (helper ? 192 : 128) * (m1 >> 2);
  const int d1 = 160 * (m1 & 3), flip = m1 >= 7;
  const int a1bytes = helper ? 24576 : 16384;
  auto load_a1 = [&](int st, int kb) {
    mbar_expect(full0 + 8 * st, a1bytes);
    tma4d_ef(sbase + st * STAGE, helper ? &maps.w1b : &maps.w1a, 4 * (kb >> 3), 16 * (kb & 7), f1 >> 6, full0 + 8 * st);
  };

  uint32_t bia[4];
  if (wg < 2) {
    const int fa = f1 + (helper ? 128 : 64) * (wg ^ flip) + 16 * (wp & 3) + g, fb = helper ? f1 + 64 + 16 * (wp & 3) + g : fa;
#pragma unroll
    for (int i = 0; i < 4; i++) asm volatile("ld.global.nc.u16 %0, [%1];" : "=r"(bia[i]) : "l"(p.b1 + (i < 2 ? fa : fb) + 8 * (i & 1)) : "memory");
  }
  if (rows) {
#pragma unroll
    for (int kk = 0; kk < 4; kk++) af[kk] = __ldg(p.tab + TB_E + kk * 128 + t128);
    const uint4 c0 = lds4(sbase + O_ST + tid * 16), c1 = lds4(sbase + O_ST + 6144 + tid * 16);
    const uint2 c2 = lds2(sbase + O_ST + 12288 + tid * 8);
    const uint32_t tc[4] = {c0.x, c0.y, c0.z, c0.w}, sy[6] = {c1.x, c1.y, c1.z, c1.w, c2.x, c2.y};
    const uint32_t l8 = pin(8 * l), syl = pin(sbase + O_Y + wp * 2336 + 8 * l);
    uint32_t sh3[3], ham[3];
#pragma unroll
    for (int k = 0; k < 3; k++) {
      const int pos = k && (l >> 4) == k - 1 ? (l & 8) + 4 * (l & 1) + ((l >> 1) & 3) : 4 * (l & 3) + ((l >> 2) & 3);
      const int sw = 2 * cta + ((wp >> 1) & 1), ph = pos ^ ((sw & 3) << 2);
      sh3[k] = pin((l >> 4) * 256 + (wp & 3) * 64 + ph * 4);
      ham[k] = pin(((ph ^ sw) & 7) == 0 ? ~1u : ~0u);
    }
    unsigned* const hh3 = upin(sc->cnt + C_H3 + (cta >> 4));
    uint8_t* const h3g = pin(sc->h3 + (cta >> 4) * (18 * 4096) + (cta & 15) * 256 + (l >> 4) * 3840);
    const int slot = 4 * (cta >> 4) + ((cta >> 1) & 3) + 32 * (2 * ((cta >> 3) & 1) + (cta & 1));
    const uint32_t* zin = sc->z2 + (size_t)slot * 4800;
    if (wg == 2) {
      {
        uint4 v[4];
        const int i3 = min(t128 + 384, 431);
        int it = 0;
        while (true) {
          uint32_t bad = 0;
#pragma unroll
          for (int k = 0; k < 4; k++) v[k] = ld_rlx4(sc->mod + 4 * (k < 3 ? t128 + 128 * k : i3));
#pragma unroll
          for (int k = 0; k < 4; k++) {
            v[k].x ^= tag16; v[k].y ^= tag16; v[k].z ^= tag16; v[k].w ^= tag16;
            bad |= v[k].x | v[k].y | v[k].z | v[k].w;
          }
          if (!any(bad & 0xffffu) || ++it > SPIN_MAX) break;
        }
#pragma unroll
        for (int k = 0; k < 4; k++) sts4(sbase + O_MOD + 16 * (k < 3 ? t128 + 128 * k : i3), v[k].x, v[k].y, v[k].z, v[k].w);
      }
      CK(14);
      bulk_commit_wait();
      bar_sync(10, NTHR);
      mbar_wait(full0 + 8 * B_Z2, 0);
      if (elect()) {
        load_a1(wp - 8, wp - 8);
      }
      __syncwarp();
    } else {
      const uint4 e0 = lds4(sbase + O_ST + 15360 + tid * 16), e1 = lds4(sbase + O_ST + 19456 + tid * 16), e2 = lds4(sbase + O_ST + 23552 + tid * 16);
      const uint32_t li[9] = {e0.x, e0.y, e0.z, e0.w, e1.x, e1.y, e1.z, e1.w, e2.x}, lx = e2.y, sb3 = e2.z;
      bar_arrive(10, NTHR);
      CK(14);
      if (wp == 1) {
        const uint32_t* zu = upin(zin);
        if (elect()) mbar_expect(full0 + 8 * B_Z2, 19200);
        wait_cnt(sc->cnt + C_Z2, 120 * ep - 40 * STRESS);
        if (elect()) {
          bulk_ld(sbase + O_IN, zu, 19200, full0 + 8 * B_Z2);
          TS(14);
        }
        __syncwarp();
      }
      mbar_wait(full0 + 8 * B_Z2, 0);
      CK(15);
      if (tid == 0) TS(11);
      uint2 v[10];
#pragma unroll
      for (int k1 = 0; k1 < 10; k1++) v[k1] = lds2(k1 < 9 ? li[k1] : lx);
      auto bad3 = [&]() {
        return any(or3(or3(diff2(v[0].x, v[1].x, tag1), diff2(v[2].x, v[3].x, tag1), diff2(v[4].x, v[5].x, tag1)), diff2(v[6].x, v[7].x, tag1), diff2(v[8].x, v[9].x, tag1)) & 1);
      };
      if (__builtin_expect(bad3(), 0)) {
        FAILCNT(1);
        int it = 0;
        do {
#pragma unroll
          for (int k1 = 0; k1 < 10; k1++) v[k1] = ld_rlx2(reinterpret_cast<const uint8_t*>(zin) + ((k1 < 9 ? li[k1] : lx) - (sbase + O_IN)));
        } while (bad3() && ++it < SPIN_MAX);
      }
      float2 za[9], zb[9];
#pragma unroll
      for (int i = 0; i < 9; i++) { za[i] = make_float2(bf_lo(v[i].x), bf_hi(v[i].x)); zb[i] = make_float2(bf_lo(v[i].y), bf_hi(v[i].y)); }
      if ((wp & 3) == wg) {
        const float sp = g ? 0.f : 1.f;
#pragma unroll
        for (int k = 1; k < 5; k++) {
          float2 a = za[k], b = za[9 - k];
          za[k] = make_float2(fmaf(-sp, b.x, a.x), fmaf(sp, b.y, a.y)); za[9 - k] = make_float2(fmaf(sp, a.x, b.x), fmaf(-sp, a.y, b.y));
          a = zb[k]; b = zb[9 - k];
          zb[k] = make_float2(fmaf(-sp, b.x, a.x), fmaf(sp, b.y, a.y)); zb[9 - k] = make_float2(fmaf(sp, a.x, b.x), fmaf(-sp, a.y, b.y));
        }
        za[0].y = g ? za[0].y : bf_lo(v[9].x); zb[0].y = g ? zb[0].y : bf_lo(v[9].y);
      }
      dft9(za); dft9(zb);
#pragma unroll
      for (int n = 0; n < 8; n += 2) {
        const int i0 = (9 - n) % 9, i1 = 8 - n;
        stmatrix4(sb3 + n * 2048, pack_bf16(za[i0].x, zb[i0].x), pack_bf16(za[i0].y, zb[i0].y), pack_bf16(za[i1].x, zb[i1].x), pack_bf16(za[i1].y, zb[i1].y));
      }
      stmatrix2(sb3 + 8 * 2048, pack_bf16(za[1].x, zb[1].x), pack_bf16(za[1].y, zb[1].y));
      fence_async_smem();
    }
    CK(16);
    __syncthreads();
    CK(17);
    float acc[24];
    const uint32_t db = (((sbase + O_B3 + wg * 6144) & 0x3FFFF) >> 4) | ((128 >> 4) << 16);
    wg_fence();
#pragma unroll
    for (int kk = 0; kk < 4; kk++) wgmma_rs_48(acc, af[kk].x, af[kk].y, af[kk].z, af[kk].w, db + kk * 16, 1024 >> 4, kk);
    wg_commit();
    uint32_t ga[9];
    if (wg < 2) {
#pragma unroll
      for (int i = 0; i < 9; i++) { const uint2 v = lds2(l8 + sbase + O_MOD + 256 * i); ga[i] = __byte_perm(v.x, v.y, 0x7632); }
    }
    wg_wait<0>();
    reg_fence(acc);
    CK(18);
#pragma unroll
    for (int i = 0; i < 3; i++) {
      const float* a = &acc[8 * i];
      const uint32_t a0 = pack_bf16(a[0], a[1]), a1 = pack_bf16(a[2], a[3]), a2 = pack_bf16(a[4], a[5]), a3 = pack_bf16(a[6], a[7]);
#pragma unroll
      for (int jh = 0; jh < 2; jh++) {
        float y[4];
        mma16<false>(y, a0, a1, a2, a3, tc[2 * jh], tc[2 * jh + 1]);
        sts(sy[2 * i] + jh * (4 * 584 * 4), pack_bf16(y[0], y[1]));
        sts(sy[2 * i + 1] + jh * (4 * 584 * 4), pack_bf16(y[2], y[3]));
      }
    }
    CK(19);
    if (wg == 2) bar_arrive(7, NTHR); else bar_sync(7, NTHR);
    if (wg) bar_sync(15, NTHR);
    if (wg < 2) {
      CK(20);
      uint2 y[9], sh[9], sw[9];
#pragma unroll
      for (int i = 0; i < 9; i++) y[i] = lds2(syl + 256 * i);
      uint32_t sel = 0x5410, sto = sbase + O_B3 + wg * 9216;
#pragma unroll 1
      for (int e = 0; e < 2; e++, sel = 0x7632, sto += 4608) {
        float a[18];
#pragma unroll
        for (int i = 0; i < 9; i++) {
          const uint32_t x1 = hfma2(ga[i], __byte_perm(y[i].x, y[i].y, sel), xr[i]);
          xr[i] = xr[9 + i]; xr[9 + i] = x1;
          a[2 * i] = bf_lo(x1); a[2 * i + 1] = bf_hi(x1);
        }
#pragma unroll
        for (int i = 0; i < 9; i++) { lds2_if(!e, sh[i], l8 + sbase + O_MOD + 4 * D_ + 256 * i); lds2_if(!e, sw[i], l8 + sbase + O_MOD + 8 * D_ + 256 * i); }
        float oa, ra;
        ln_stats1(a, 1.0f, oa, ra);
#pragma unroll
        for (int i = 0; i < 9; i++) {
          a[2 * i] = fmaf(fmaf(a[2 * i], ra, oa), __uint_as_float(sw[i].x), __uint_as_float(sh[i].x));
          a[2 * i + 1] = fmaf(fmaf(a[2 * i + 1], ra, oa), __uint_as_float(sw[i].y), __uint_as_float(sh[i].y));
        }
        ln_stats1(a, 0.5f, oa, ra);
        uint32_t hv[9];
#pragma unroll
        for (int i = 0; i < 9; i++) hv[i] = bitsel(pack_bf16(fmaf(a[2 * i], ra, oa), fmaf(a[2 * i + 1], ra, oa)), ham[i == 2 ? 1 : i == 6 ? 2 : 0], tag1);
        if (!(wg | e)) {
          if (elect()) red_add(hh3, 1);
#pragma unroll
          for (int i = 0; i < 9; i++) asm volatile("st.global.b32 [%0], %1;" ::"l"(h3g + sh3[i == 2 ? 1 : i == 6 ? 2 : 0] + i * 8192), "r"(hv[i]) : "memory");
          bar_arrive(15, NTHR);
          if (tid == 0) TS(13);
        } else {
#pragma unroll
          for (int i = 0; i < 9; i++) sts(sto + sh3[i == 2 ? 1 : i == 6 ? 2 : 0] + i * 512, hv[i]);
        }
        if (!e) bar_arrive(8, 288);
        CK(21 + e);
      }
      fence_async_smem();
      bar_arrive(9, 288);
      CK(23);
    }
  }

  const bool g2 = rows;
  const int z2 = cta, r = z2 >> 6;
  const int s2 = 128 * ((z2 >> 2) & 15), d2 = 144 * (z2 & 3);
  constexpr int ST0 = (32 - JSK - 1) % NST, ST1 = 31 % NST;

  if (wg == 2) {
    asm volatile("setmaxnreg.dec.sync.aligned.u32 40;");
    auto load_b = [&](bool second, int i, int st) {
      const uint32_t lb = full0 + 8 * (B_LAND + st), bytes = second ? 18432 : STAGE - a1bytes;
      mbar_expect(lb, bytes);
      bulk_ld(sbase + (second ? st * STAGE2 + 16384 : st * STAGE + a1bytes),
              second ? sc->u + ((size_t)(36 * r + kb2_order(i)) * D_ + d2) * 128 : sc->h3 + ((size_t)(i * 18 + (d1 >> 5)) << 12), bytes, lb);
    };
    if (wp == 8) {
      int st = rows ? 4 : 0, ph = 1;
#pragma unroll 1
      for (int kb = st; kb < 32; kb++) {
        if (rows && (kb >> 1) == 2) mbar_wait(full0 + 8 * (B_S4 - 4 + kb), 0);
        mbar_wait(empty0 + 8 * st, ph);
        if (elect()) {
          load_a1(st, kb);
        }
        __syncwarp();
        ring_next<false>(st, ph);
      }
      if (g2) {
        st++;
#pragma unroll 1
        for (int i = 0; i < 36; i++) {
          if (i == HOLDA) mbar_wait(full0 + 8 * B_GO, 0);
          mbar_wait(empty0 + 8 * st, ph);
          if (elect()) {
            mbar_expect(full0 + 8 * st, 16384);
            tma3d_ef(sbase + st * STAGE2, &maps.w2, 64 * (36 * r + kb2_order(i)), s2 >> 6, full0 + 8 * st);
          }
          __syncwarp();
          ring_next<true>(st, ph);
        }
      }
    } else if (wp >= 10) {
      const int sw = wp - 10;
      if (sw) {
        if (rows) {
          bar_sync(8, 288);
          mbar_wait(full0 + 8 * H3W, 0);
          if (elect()) mbar_arrive(full0 + 8 * B_S4);
          bar_sync(9, 288);
          if (elect()) tma_st3d(&maps.h3, sbase + O_B3 + 4608, 64 * (cta & 15), 18 * (cta >> 4), 1);
          bulk_commit_wait();
          if (elect()) {
            red_add(sc->cnt + C_H3 + (cta >> 4) + 8, 4);
            mbar_arrive(full0 + 8 * B_S5); mbar_arrive(full0 + 8 * B_S5);
            TS(24);
            asm volatile("fence.acq_rel.gpu;" ::: "memory");
            red_add(&sc->cnt[C_X + 64], 1);
          }
          __syncwarp();
        }
        if (g2) {
          uint2 v[3];
          int it = 0;
          do {
#pragma unroll
            for (int i = 0; i < 3; i++) v[i] = ld_rlx2(sc->mod + 3 * D_ + d2 + 2 * min(l + 32 * i, 71));
          } while (any(or3(diff2(v[0].x, v[0].y, tag16), diff2(v[1].x, v[1].y, tag16), diff2(v[2].x, v[2].y, tag16)) & 0xffffu) && ++it < SPIN_MAX);
#pragma unroll
          for (int i = 0; i < 3; i++) sts(sbase + O_GB + 4 * min(l + 32 * i, 71), __byte_perm(v[i].x, v[i].y, 0x7632));
          __syncwarp();
        }
        wait_cnt<true>(&sc->cnt[C_X + 64], 128 * ep);
        if (elect()) mbar_arrive(full0 + 8 * B_X);
        __syncwarp();
      }
      uint32_t lph = 0;
      auto check_tiles = [&](bool second, int n, int st, uint32_t o1, uint32_t d2nd) {
        const uint32_t b1 = pin(sbase + o1), b2 = pin(sbase + o1 + d2nd);
        int i = 0, it = 0;
#pragma unroll 1
        do {
          const uint32_t so = st * (second ? STAGE2 : STAGE);
          mbar_wait(full0 + 8 * (B_LAND + st), (lph >> st) & 1);
          lph ^= 1u << st;
          uint32_t v[20];
#pragma unroll
          for (int k = 0; k < 20; k++) if (!second || k < 10 || k >= 12) v[k] = lds(k < 12 ? b1 + so + k * 1024 : b2 + so + (k - 12) * 1024); else v[k] = tag1;
#pragma unroll
          for (int k = 0; k < 10; k++) v[k] = diff2(v[2 * k], v[2 * k + 1], tag1);
          const uint32_t bad = or3(or3(or3(v[0], v[1], v[2]), or3(v[3], v[4], v[5]), v[6]), v[7], or3(v[8], v[9], 0));
          if (__builtin_expect(any(bad & 1) && ++it < SPIN_MAX, 0)) {
            FAILCNT(2 + second);
            fence_async_smem();
            __syncwarp();
            if (elect()) load_b(second, i, st);
            __syncwarp();
            continue;
          }
          if (elect()) mbar_arrive(full0 + 8 * st);
          if (++st == NST) st = 0;
          i++;
        } while (i < n);
      };
      if (!sw) check_tiles(false, NV1, 0, a1bytes + l * 32 + (l >> 2) * 4, helper ? 4096 : 12288);
      const bool first = helper || m1 < W0N;
#pragma unroll 1
      for (int k = sw ? first : !first; k <= sw; k++) {
        const uint32_t stg = sbase + (!k ? ST0 * STAGE : helper ? ST1 * STAGE : O_U1);
        const int kbA = (f1 >> 6) + (helper ? 2 : 1) * (k ^ flip), kbB = helper ? (f1 >> 6) + 1 : kbA;
        uint8_t* const uA = upin(sc->u + ((size_t)kbA * D_ + d1) * 128);
        uint8_t* const uB = upin(sc->u + ((size_t)kbB * D_ + (helper ? d1 : d1 + 96)) * 128);
        unsigned* const fA = pin(sc->cnt + C_U + kb2_pos(kbA));
        unsigned* const fB = pin(sc->cnt + C_U + kb2_pos(kbB));
        const bool slow = sw && !helper;
        bar_sync(11 + k, 160);
        if (!slow) { if (elect()) { bulk_st(uA, stg, 96 * 128); TS(k ? 31 : 30); } __syncwarp(); }
        bar_sync(13 + k, 160);
        if (slow) {
          if (g2) mbar_wait(full0 + 8 * B_GO, 0);
          if (first) pause(10 * TRK0);
#pragma unroll 1
          for (int i = 0; i < 20480; i += 2048) {
            if (elect()) bulk_st(uA + i, stg + i, 2048);
            pause(k ? TRKC : TRK0);
          }
        }
        if (elect()) red_add(fA, 1);
        if ((helper ? k : !slow) && elect()) bulk_st(uB, stg + 96 * 128, helper ? 96 * 128 : 64 * 128);
        bulk_commit_wait();
        if (helper && k && elect()) red_add(fB, 1);
        if (elect()) {
          if (!k || helper) mbar_arrive(empty0 + 8 * (k ? ST1 : ST0));
          TS(k ? 23 : 17);
          mbar_arrive(full0 + 8 * B_S5);
        }
        __syncwarp();
      }
      if (sw) {
        mbar_wait(full0 + 8 * B_S5, rows);
        if (elect()) { asm volatile("fence.acq_rel.gpu;" ::: "memory"); red_add(&sc->cnt[C_X], 1); }
        __syncwarp();
      }
      if (g2) {
        if (!sw) check_tiles(true, NV2, 3, 16384 + l * 32 + (4 * (g & 1) + (g >> 1)) * 4, 10240);
        else {
          wait_cnt<true>(&sc->cnt[C_X], NCTA * ep);
          if (elect()) mbar_arrive(full0 + 8 * B_X);
          if (cta == 0) sc->cnt[C_EP + (pin(l) ^ 1)] = ep;
          __syncwarp();
        }
      }
      __syncwarp();
    } else {
      uint32_t ready = 0;
      int st = 0, ph = 1;
#pragma unroll 1
      for (int kb = 0; kb < 32; kb++) {
        const uint8_t* src = upin(sc->h3 + ((size_t)(kb * 18 + (d1 >> 5)) << 12));
        const uint32_t dst = upin(sbase + st * STAGE + a1bytes), lb = full0 + 8 * ((kb < NV1 ? B_LAND : 0) + st);
        if (kb == NV1) { mbar_wait(full0 + 8 * B_X, 0); fence_async_glb(); ready = ~0u; }
        if (rows && (kb >> 1) == 2) mbar_wait(full0 + 8 * (B_S4 - 4 + kb), 0);
        mbar_wait(empty0 + 8 * st, ph);
        if (elect()) mbar_expect(lb, STAGE - a1bytes);
        wait_flags(sc->cnt + C_H3 + l, (kb & 7) + (kb < 8 ? 0 : 8), 64 * ep - 24 * STRESS, ready);
        if (elect()) bulk_ld(dst, src, STAGE - a1bytes, lb);
        ring_next<false>(st, ph);
      }
      if (g2) {
        ready = 0;
        st++;
#pragma unroll 1
        for (int i = 0; i < 36; i++) {
          const int kb = kb2_order(i);
          const uint8_t* src = upin(sc->u + ((size_t)(36 * r + kb) * D_ + d2) * 128);
          const uint32_t dst = upin(sbase + st * STAGE2 + 16384), lb = full0 + 8 * ((i < NV2 ? B_LAND : 0) + st);
          if (i == NV2) { mbar_wait(full0 + 8 * B_X, 1); fence_async_glb(); ready = ~0u; }
          mbar_wait(empty0 + 8 * st, ph);
          if (elect()) mbar_expect(lb, 18432);
          wait_flags(sc->cnt + C_U + 64 * r + l, i & 31, 4 * ep - 2 * STRESS, ready);
          if (elect()) {
            bulk_ld(dst, src, 18432, lb);
            if (i == GOAT) mbar_arrive(full0 + 8 * B_GO);
          }
          ring_next<true>(st, ph);
        }
      }
    }
  } else {
    asm volatile("setmaxnreg.inc.sync.aligned.u32 232;");
    const int wgu = wg;
    constexpr uint32_t sb4 = sbase >> 4;
    const int w = wp & 3;
    Ring rg = {0, 0};
    uint32_t* const x1p = p.out + (size_t)(cta + 128 * ((wp & 3) + 8 * wg)) * 288 + l;
    const uint32_t ad = pin(sbase + (!wg ? ST0 * STAGE : helper ? ST1 * STAGE : O_U1) + (8 * (l >> 4) + (l & 7)) * 128 + (((2 * w + ((l >> 3) & 1)) ^ (l & 7)) << 4));
    const uint32_t uam = pin(g == 2 * t ? 0xfffefffeu : ~0u), uom = tag1 * 0x10001u;
    float acc[96];
    constexpr uint32_t LA = (8192 >> 4) << 16, LB = (4096 >> 4) << 16;
    {
      const float a0 = 0.5f * bf_lo(pin(bia[0])), a1 = 0.5f * bf_lo(pin(bia[1])), b0 = 0.5f * bf_lo(pin(bia[2])), b1 = 0.5f * bf_lo(pin(bia[3]));
#pragma unroll
      for (int i = 0; i < 96; i++) acc[i] = i < 48 ? ((i & 2) ? a1 : a0) : ((i & 2) ? b1 : b0);
      reg_fence(acc);
    }
    if (!helper) gemm_main<0>(acc, sb4 + (wgu ^ flip) * 512 + LA, 0, sb4 + 1024 + LB, wgu, rg, rows, x1p, xr);
    else {
      float ac2[96];
#pragma unroll
      for (int i = 0; i < 96; i++) asm volatile("mov.b32 %0, %1;" : "=f"(ac2[i]) : "f"(acc[i]));
      gemm_main<1>(ac2, sb4 + (wgu ^ flip) * 1024 + LA, sb4 + 512 + LA, sb4 + 1536 + LB, wgu, rg, rows, x1p, xr);
#pragma unroll
      for (int i = 0; i < 96; i++) asm volatile("mov.b32 %0, %1;" : "=f"(acc[i]) : "f"(ac2[i]));
    }
    if (t128 == 0) { TS(wg ? 16 : 6); if (wg) TSC(5); }
    {
      float tp[2] = {0.f, 0.f};
#pragma unroll
      for (int j = 0; j < 12; j++) {
        const float* a = &acc[8 * j];
        const float k3 = j < 2 ? GK3 : fmaf(tp[j & 1], 0.0f, GK3);
        float o[8];
#pragma unroll
        for (int e = 0; e < 8; e++) {
          float z = a[e] * fmaf(a[e] * k3, a[e], GK1);
          asm("tanh.approx.f32 %0, %0;" : "+f"(z));
          if (e == GDEP) tp[j & 1] = z;
          o[e] = fmaf(a[e], z, a[e]);
        }
        stmatrix4t(ad + j * 2048, bitsel(pack_bf16(o[0], o[1]), uam, uom), pack_bf16(o[2], o[3]), bitsel(pack_bf16(o[4], o[5]), uam, uom), pack_bf16(o[6], o[7]));
        if (j == 5) {
          fence_async_smem();
          bar_arrive(11 + wgu, 160);
        }
        if ((j == 5 && helper && !wgu) || (j == 9 && !helper)) break;
      }
      fence_async_smem();
      bar_arrive(13 + wgu, 160);
      if (t128 == 0) TS(wg ? 29 : 28);
    }
    if (g2) {
      const int mb = wgu ^ r;
      const int odd = z2 & 1;
      uint4 gq[4];
      uint2 gs;
      {
        float a0 = 0.f, a1 = 0.f;
        if (wgu) { a0 = __bfloat162float(p.b2[s2 + 64 * mb + 16 * w + g]); a1 = __bfloat162float(p.b2[s2 + 64 * mb + 16 * w + 8 + g]); }
#pragma unroll
        for (int i = 0; i < 4; i++) gq[i] = lds4(sbase + O_GB + 32 * odd + 64 * i + 16 * t);
        gs = lds2(sbase + O_GB + (odd ? 0 : 256) + 8 * t);
#pragma unroll
        for (int i = 0; i < 72; i++) acc[i] = (i & 2) ? a1 : a0;
      }
      uint32_t* const ob = p.out + (size_t)(s2 + 64 * mb + 16 * w + g) * 288 + (d2 >> 1);
      uint32_t* const oq = pin(ob + 8 * odd + 4 * t);
      uint32_t* const os = pin(ob + (odd ? 0 : 64) + 2 * t);
      rg.st++;
      gemm_main<3>(acc, sb4 + mb * 512 + LA, 0, sb4 + 1024 + (1 << 16), wgu, rg, rows, x1p, xr);
      if (t128 == 0) { TS(wg ? 20 : 19); if (wg) TSC(22); }
      auto finish = [&](const float* aq, const float* as) {
#pragma unroll
        for (int i = 0; i < 8; i++) {
          const float* a = aq + 16 * (i >> 1) + 2 * (i & 1);
          const uint4 gv = gq[i >> 1];
          red_bf16x8(oq + (i & 1) * 2304 + 16 * (i >> 1), hmul2(gv.x, pack_bf16(a[0], a[1])), hmul2(gv.y, pack_bf16(a[4], a[5])),
                     hmul2(gv.z, pack_bf16(a[8], a[9])), hmul2(gv.w, pack_bf16(a[12], a[13])));
        }
#pragma unroll
        for (int i = 0; i < 2; i++) red_bf16x4(os + i * 2304, hmul2(gs.x, pack_bf16(as[2 * i], as[2 * i + 1])), hmul2(gs.y, pack_bf16(as[2 * i + 4], as[2 * i + 5])));
      };
      if (odd) finish(&acc[8], &acc[0]); else finish(&acc[0], &acc[64]);
      if (t128 == 0) TS(wg ? 7 : 21);
      __syncwarp();
    }
  }
}

typedef CUresult (*EncodeFn)(CUtensorMap*, CUtensorMapDataType, cuuint32_t, void*, const cuuint64_t*, const cuuint64_t*, const cuuint32_t*,
                             const cuuint32_t*, CUtensorMapInterleave, CUtensorMapSwizzle, CUtensorMapL2promotion, CUtensorMapFloatOOBfill);

struct Dim { cuuint64_t n, stride; cuuint32_t box; };
template <int RANK>
void make_map(EncodeFn enc, CUtensorMap* m, bool words, int swz, const void* ptr, const Dim (&d)[RANK]) {
  cuuint64_t gd[RANK], gs[RANK];
  cuuint32_t bx[RANK], es[RANK];
  for (int i = 0; i < RANK; i++) { gd[i] = d[i].n; gs[i] = d[i].stride; bx[i] = d[i].box; es[i] = 1; }
  enc(m, words ? CU_TENSOR_MAP_DATA_TYPE_UINT32 : CU_TENSOR_MAP_DATA_TYPE_BFLOAT16, RANK, const_cast<void*>(ptr), gd, gs + 1, bx, es,
      CU_TENSOR_MAP_INTERLEAVE_NONE, static_cast<CUtensorMapSwizzle>(swz),
      swz == 3 ? CU_TENSOR_MAP_L2_PROMOTION_L2_256B : CU_TENSOR_MAP_L2_PROMOTION_NONE, CU_TENSOR_MAP_FLOAT_OOB_FILL_NONE);
}

}

extern "C" void kernel_launch(void* const* d_in, const int* in_sizes, int n_in, void* d_out, int out_size) {
  (void)in_sizes; (void)n_in; (void)out_size;
  static EncodeFn enc = nullptr;
  static void *sptr = nullptr, *tptr = nullptr;
  if (!enc) {
    void* f = nullptr; cudaDriverEntryPointQueryResult qr;
    cudaGetDriverEntryPoint("cuTensorMapEncodeTiled", &f, cudaEnableDefault, &qr);
    enc = reinterpret_cast<EncodeFn>(f);
    cudaFuncSetAttribute(fused_kernel, cudaFuncAttributeMaxDynamicSharedMemorySize, SMEM_BYTES);
    cudaGetSymbolAddress(&sptr, g_s);
    cudaGetSymbolAddress(&tptr, T_TAB);
  }
  Params p;
  p.x = (const __nv_bfloat16*)d_in[0]; p.wr = (const __nv_bfloat16*)d_in[1]; p.wi = (const __nv_bfloat16*)d_in[2];
  p.b1 = (const __nv_bfloat16*)d_in[5]; p.b2 = (const __nv_bfloat16*)d_in[7];
  p.c = (const __nv_bfloat16*)d_in[8]; p.wmod = (const __nv_bfloat16*)d_in[9];
  p.w1 = (const __nv_bfloat16*)d_in[4]; p.w2 = (const __nv_bfloat16*)d_in[6];
  p.out = static_cast<uint32_t*>(d_out); p.s = static_cast<Scratch*>(sptr); p.tab = static_cast<const uint4*>(tptr);
  Maps maps;
  make_map<4>(enc, &maps.w1a, false, 3, p.w1, {{64, 0, 64}, {16, 128 * 2 * F_, 4}, {128, 2 * F_, 16}, {72, 128, 2}});
  make_map<4>(enc, &maps.w1b, false, 3, p.w1, {{64, 0, 64}, {16, 128 * 2 * F_, 4}, {128, 2 * F_, 16}, {72, 128, 3}});
  make_map<3>(enc, &maps.w2, false, 3, p.w2, {{64, 0, 64}, {F_, 2 * S_, 64}, {32, 128, 2}});
  make_map<2>(enc, &maps.z1, true, 0, p.s->z1, {{5120, 0, 40}, {120, 20480, 60}});
  for (int i = 0; i < 2; i++) make_map<2>(enc, &maps.z2[i], true, 0, p.s->z2, {{4800, 0, i ? 16u : 24u}, {128, 19200, 128}});
  for (int i = 0; i < 4; i++) make_map<2>(enc, &maps.wf[i], false, 2 - (i & 1), (i & 2) ? p.wi : p.wr, {{16 * DF_, 0, (i & 1) ? 16u : 32u}, {128, 32 * DF_, 128}});
  make_map<2>(enc, &maps.wm, false, 1, p.wmod, {{6 * D_, 0, 16}, {D_, 12 * D_, 192}});
  make_map<3>(enc, &maps.h3, true, 0, p.s->h3, {{1024, 0, 64}, {144, 4096, 18}, {4, 144 * 4096, 3}});
  fused_kernel<<<NCTA, NTHR, SMEM_BYTES, cudaStreamPerThread>>>(p, maps);
}
```

```cpp
#include <cuda_runtime.h>
#include <cuda_bf16.h>
#include <cuda.h>
#include <stdint.h>

namespace {

constexpr int S_ = 2048, D_ = 576, DF_ = 289, F_ = 4608;
constexpr int NCTA = 132, NTHR = 384;
constexpr int STAGE = 36864, NST = 6;
constexpr int STAGE2 = 34816, O_U1 = NST * STAGE2, O_GB = O_U1 + 20480, SMEM_BYTES = 232448;
constexpr uint32_t sbase = 1024, red = sbase + NST * STAGE, full0 = sbase + SMEM_BYTES - 256, empty0 = full0 + 8 * NST;
constexpr int O_NRM = 0, O_B1 = 19456, O_Z1 = 38912, O_P2 = 59392, O_ST = 3 * STAGE;
constexpr int O_RAW = 4 * STAGE;
constexpr int O_IN = 4 * STAGE, O_Y = O_IN + 19456, O_B3 = O_IN + 38912, O_MOD = O_IN + 57344;

__device__ __align__(128) const uint32_t T_TAB[5632] = {
0x3f803f80,0xbf803f80,0x3f803f80,0xbf803f80,0x3f803f80,0xbf803f80,0x3f803f80,0xbf803f80,0x3f803f80,0xbf803f80,0x3f803f80,0xbf803f80,
0x3f803f80,0xbf803f80,0x3f803f80,0xbf803f80,0x3f7f3f80,0xbdc90000,0x3f223f35,0xbf46bf35,0x3f753f7b,0xbe95be48,0x3ef13f0e,0xbf62bf55,
0x3f623f6d,0xbef1bec4,0x3e953ec4,0xbf75bf6d,0x3f463f55,0xbf22bf0e,0x3dc93e48,0xbf7fbf7b,0x3f7b3f80,0xbe480000,0xbe480000,0xbf7bbf80,
0x3f553f6d,0xbf0ebec4,0xbf0ebec4,0xbf55bf6d,0x3f0e3f35,0xbf55bf35,0xbf55bf35,0xbf0ebf35,0x3e483ec4,0xbf7bbf6d,0xbf7bbf6d,0xbe48bec4,
0x3f753f80,0xbe950000,0xbf62bf35,0xbef1bf35,0x3f223f55,0xbf46bf0e,0xbf7fbf7b,0x3dc9be48,0x3dc93ec4,0xbf7fbf6d,0xbf46bf6d,0x3f223ec4,
0xbef1be48,0xbf62bf7b,0xbe95bf0e,0x3f753f55,0x3f6d3f80,0xbec40000,0xbf6dbf80,0x3ec40000,0x3ec43f35,0xbf6dbf35,0xbec4bf35,0x3f6d3f35,
0xbec40000,0xbf6dbf80,0x3ec40000,0x3f6d3f80,0xbf6dbf35,0xbec4bf35,0x3f6d3f35,0x3ec43f35,0x3f623f80,0xbef10000,0xbe95bf35,0x3f753f35,
0x3dc93f0e,0xbf7fbf55,0x3f223e48,0x3f463f7b,0xbf46bec4,0xbf22bf6d,0x3f7f3f6d,0xbdc93ec4,0xbf75bf7b,0x3e95be48,0x3ef13f55,0xbf62bf0e,
0x3f553f80,0xbf0e0000,0x3f0e0000,0x3f553f80,0xbe483ec4,0xbf7bbf6d,0x3f7b3f6d,0xbe483ec4,0xbf7bbf35,0xbe48bf35,0x3e483f35,0xbf7bbf35,
0xbf0ebf6d,0x3f553ec4,0xbf55bec4,0xbf0ebf6d,0x3f463f80,0xbf220000,0x3f7f3f35,0x3dc93f35,0xbef13e48,0xbf62bf7b,0x3e953f55,0xbf75bf0e,
0xbf75bf6d,0x3e95bec4,0xbf62bec4,0xbef1bf6d,0x3dc9bf0e,0x3f7f3f55,0xbf22bf7b,0x3f463e48,0x3f353f80,0xbf350000,0x3f353f80,0xbf350000,
0xbf350000,0xbf35bf80,0xbf350000,0xbf35bf80,0xbf35bf80,0x3f350000,0xbf35bf80,0x3f350000,0x3f350000,0x3f353f80,0x3f350000,0x3f353f80,
0x3f223f80,0xbf460000,0xbdc93f35,0xbf7fbf35,0xbf62be48,0xbef1bf7b,0xbf75bf55,0x3e95bf0e,0xbe95bf6d,0x3f753ec4,0x3ef1bec4,0x3f623f6d,
0x3f7f3f0e,0x3dc93f55,0x3f463f7b,0xbf223e48,0x3f0e3f80,0xbf550000,0xbf550000,0xbf0ebf80,0xbf7bbec4,0xbe48bf6d,0xbe48bf6d,0x3f7b3ec4,
0x3e48bf35,0x3f7b3f35,0x3f7b3f35,0xbe483f35,0x3f553f6d,0xbf0e3ec4,0xbf0e3ec4,0xbf55bf6d,0x3ef13f80,0xbf620000,0xbf75bf35,0x3e95bf35,
0xbf7fbf0e,0x3dc9bf55,0x3f46be48,0x3f223f7b,0x3f22bec4,0x3f463f6d,0x3dc93f6d,0xbf7fbec4,0x3e953f7b,0xbf75be48,0xbf62bf55,0x3ef1bf0e,
0x3ec43f80,0xbf6d0000,0xbec4bf80,0x3f6d0000,0xbf6dbf35,0x3ec4bf35,0x3f6d3f35,0xbec43f35,0x3f6d0000,0x3ec43f80,0xbf6d0000,0xbec4bf80,
0xbec43f35,0xbf6dbf35,0x3ec4bf35,0x3f6d3f35,0x3e953f80,0xbf750000,0x3ef1bf35,0x3f623f35,0xbf46bf55,0x3f22bf0e,0x3dc93f7b,0xbf7fbe48,
0x3f7f3ec4,0xbdc93f6d,0xbf22bf6d,0x3f46bec4,0xbf623e48,0xbef1bf7b,0x3f753f0e,0xbe953f55,0x3e483f80,0xbf7b0000,0x3f7b0000,0x3e483f80,
0xbf0ebf6d,0x3f55bec4,0xbf553ec4,0xbf0ebf6d,0x3f553f35,0xbf0e3f35,0x3f0ebf35,0x3f553f35,0xbf7bbec4,0x3e48bf6d,0xbe483f6d,0xbf7bbec4,
0x3dc93f80,0xbf7f0000,0x3f463f35,0xbf223f35,0xbe95bf7b,0x3f75be48,0xbf62bf0e,0x3ef1bf55,0x3ef13f6d,0xbf623ec4,0x3f753ec4,0xbe953f6d,
0xbf22bf55,0x3f46bf0e,0xbf7fbe48,0x3dc9bf7b,0x3f80,0xbf800000,0x3f80,0xbf800000,0xbf80,0x3f800000,0xbf80,0x3f800000,
0x3f80,0xbf800000,0x3f80,0xbf800000,0xbf80,0x3f800000,0xbf80,0x3f800000,0xbdc93f80,0xbf7f0000,0xbf463f35,0xbf22bf35,
0x3e95bf7b,0x3f753e48,0x3f62bf0e,0x3ef13f55,0xbef13f6d,0xbf62bec4,0xbf753ec4,0xbe95bf6d,0x3f22bf55,0x3f463f0e,0x3f7fbe48,0x3dc93f7b,
0xbe483f80,0xbf7b0000,0xbf7b0000,0x3e48bf80,0x3f0ebf6d,0x3f553ec4,0x3f553ec4,0xbf0e3f6d,0xbf553f35,0xbf0ebf35,0xbf0ebf35,0x3f55bf35,
0x3f7bbec4,0x3e483f6d,0x3e483f6d,0xbf7b3ec4,0xbe953f80,0xbf750000,0xbef1bf35,0x3f62bf35,0x3f46bf55,0x3f223f0e,0xbdc93f7b,0xbf7f3e48,
0xbf7f3ec4,0xbdc9bf6d,0x3f22bf6d,0x3f463ec4,0x3f623e48,0xbef13f7b,0xbf753f0e,0xbe95bf55,0xbec43f80,0xbf6d0000,0x3ec4bf80,0x3f6d0000,
0x3f6dbf35,0x3ec43f35,0xbf6d3f35,0xbec4bf35,0xbf6d0000,0x3ec4bf80,0x3f6d0000,0xbec43f80,0x3ec43f35,0xbf6d3f35,0xbec4bf35,0x3f6dbf35,
0xbef13f80,0xbf620000,0x3f75bf35,0x3e953f35,0x3f7fbf0e,0x3dc93f55,0xbf46be48,0x3f22bf7b,0xbf22bec4,0x3f46bf6d,0xbdc93f6d,0xbf7f3ec4,
0xbe953f7b,0xbf753e48,0x3f62bf55,0x3ef13f0e,0xbf0e3f80,0xbf550000,0x3f550000,0xbf0e3f80,0x3f7bbec4,0xbe483f6d,0x3e48bf6d,0x3f7bbec4,
0xbe48bf35,0x3f7bbf35,0xbf7b3f35,0xbe48bf35,0xbf553f6d,0xbf0ebec4,0x3f0e3ec4,0xbf553f6d,0xbf223f80,0xbf460000,0x3dc93f35,0xbf7f3f35,
0x3f62be48,0xbef13f7b,0x3f75bf55,0x3e953f0e,0x3e95bf6d,0x3f75bec4,0xbef1bec4,0x3f62bf6d,0xbf7f3f0e,0x3dc9bf55,0xbf463f7b,0xbf22be48,
0xbf353f80,0xbf350000,0xbf353f80,0xbf350000,0x3f350000,0xbf353f80,0x3f350000,0xbf353f80,0x3f35bf80,0x3f350000,0x3f35bf80,0x3f350000,
0xbf350000,0x3f35bf80,0xbf350000,0x3f35bf80,0xbf463f80,0xbf220000,0xbf7f3f35,0x3dc9bf35,0x3ef13e48,0xbf623f7b,0xbe953f55,0xbf753f0e,
0x3f75bf6d,0x3e953ec4,0x3f62bec4,0xbef13f6d,0xbdc9bf0e,0x3f7fbf55,0x3f22bf7b,0x3f46be48,0xbf553f80,0xbf0e0000,0xbf0e0000,0x3f55bf80,
0x3e483ec4,0xbf7b3f6d,0xbf7b3f6d,0xbe48bec4,0x3f7bbf35,0xbe483f35,0xbe483f35,0xbf7b3f35,0x3f0ebf6d,0x3f55bec4,0x3f55bec4,0xbf0e3f6d,
0xbf623f80,0xbef10000,0x3e95bf35,0x3f75bf35,0xbdc93f0e,0xbf7f3f55,0xbf223e48,0x3f46bf7b,0x3f46bec4,0xbf223f6d,0xbf7f3f6d,0xbdc9bec4,
0x3f75bf7b,0x3e953e48,0xbef13f55,0xbf623f0e,0xbf6d3f80,0xbec40000,0x3f6dbf80,0x3ec40000,0xbec43f35,0xbf6d3f35,0x3ec4bf35,0x3f6dbf35,
0x3ec40000,0xbf6d3f80,0xbec40000,0x3f6dbf80,0x3f6dbf35,0xbec43f35,0xbf6d3f35,0x3ec4bf35,0xbf753f80,0xbe950000,0x3f62bf35,0xbef13f35,
0xbf223f55,0xbf463f0e,0x3f7fbf7b,0x3dc93e48,0xbdc93ec4,0xbf7f3f6d,0x3f46bf6d,0x3f22bec4,0x3ef1be48,0xbf623f7b,0x3e95bf0e,0x3f75bf55,
0xbf7b3f80,0xbe480000,0x3e480000,0xbf7b3f80,0xbf553f6d,0xbf0e3ec4,0x3f0ebec4,0xbf553f6d,0xbf0e3f35,0xbf553f35,0x3f55bf35,0xbf0e3f35,
0xbe483ec4,0xbf7b3f6d,0x3f7bbf6d,0xbe483ec4,0xbf7f3f80,0xbdc90000,0xbf223f35,0xbf463f35,0xbf753f7b,0xbe953e48,0xbef13f0e,0xbf623f55,
0xbf623f6d,0xbef13ec4,0xbe953ec4,0xbf753f6d,0xbf463f55,0xbf223f0e,0xbdc93e48,0xbf7f3f7b,0x3f803f80,0xbf803f80,0x3f803f80,0xbf803f80,
0x3f803f80,0xbf803f80,0x3f803f80,0xbf803f80,0x3f803f80,0xbf803f80,0x3f803f80,0xbf803f80,0x3f803f80,0xbf803f80,0x3f803f80,0xbf803f80,
0xbdc90000,0xbf7fbf80,0xbf46bf35,0xbf22bf35,0xbe95be48,0xbf75bf7b,0xbf62bf55,0xbef1bf0e,0xbef1bec4,0xbf62bf6d,0xbf75bf6d,0xbe95bec4,
0xbf22bf0e,0xbf46bf55,0xbf7fbf7b,0xbdc9be48,0xbf7bbf80,0x3e480000,0x3e480000,0x3f7b3f80,0xbf55bf6d,0x3f0e3ec4,0x3f0e3ec4,0x3f553f6d,
0xbf0ebf35,0x3f553f35,0x3f553f35,0x3f0e3f35,0xbe48bec4,0x3f7b3f6d,0x3f7b3f6d,0x3e483ec4,0x3e950000,0x3f753f80,0x3ef13f35,0xbf62bf35,
0x3f463f0e,0x3f223f55,0xbdc93e48,0xbf7fbf7b,0x3f7f3f6d,0x3dc93ec4,0xbf22bec4,0xbf46bf6d,0x3f623f7b,0xbef1be48,0xbf75bf55,0xbe95bf0e,
0x3f6d3f80,0xbec40000,0xbf6dbf80,0x3ec40000,0x3ec43f35,0xbf6dbf35,0xbec4bf35,0x3f6d3f35,0xbec40000,0xbf6dbf80,0x3ec40000,0x3f6d3f80,
0xbf6dbf35,0xbec4bf35,0x3f6d3f35,0x3ec43f35,0xbef10000,0xbf62bf80,0x3f753f35,0x3e953f35,0xbf7fbf55,0xbdc9bf0e,0x3f463f7b,0xbf22be48,
0xbf22bf6d,0x3f463ec4,0xbdc93ec4,0xbf7fbf6d,0x3e95be48,0x3f753f7b,0xbf62bf0e,0xbef1bf55,0xbf55bf80,0x3f0e0000,0xbf0e0000,0xbf55bf80,
0x3e48bec4,0x3f7b3f6d,0xbf7bbf6d,0x3e48bec4,0x3f7b3f35,0x3e483f35,0xbe48bf35,0x3f7b3f35,0x3f0e3f6d,0xbf55bec4,0x3f553ec4,0x3f0e3f6d,
0x3f220000,0x3f463f80,0xbdc9bf35,0x3f7f3f35,0x3f623f7b,0xbef13e48,0x3f753f0e,0x3e953f55,0xbe953ec4,0xbf75bf6d,0x3ef13f6d,0xbf62bec4,
0xbf7fbf55,0x3dc9bf0e,0xbf46be48,0xbf22bf7b,0x3f353f80,0xbf350000,0x3f353f80,0xbf350000,0xbf350000,0xbf35bf80,0xbf350000,0xbf35bf80,
0xbf35bf80,0x3f350000,0xbf35bf80,0x3f350000,0x3f350000,0x3f353f80,0x3f350000,0x3f353f80,0xbf460000,0xbf22bf80,0xbf7fbf35,0x3dc9bf35,
0xbef1bf7b,0x3f623e48,0x3e95bf0e,0x3f753f55,0x3f753ec4,0x3e953f6d,0x3f623f6d,0xbef13ec4,0x3dc93f55,0xbf7fbf0e,0xbf223e48,0xbf46bf7b,
0xbf0ebf80,0x3f550000,0x3f550000,0x3f0e3f80,0x3f7b3ec4,0x3e483f6d,0x3e483f6d,0xbf7bbec4,0xbe483f35,0xbf7bbf35,0xbf7bbf35,0x3e48bf35,
0xbf55bf6d,0x3f0ebec4,0x3f0ebec4,0x3f553f6d,0x3f620000,0x3ef13f80,0xbe953f35,0xbf75bf35,0xbdc93f55,0xbf7fbf0e,0xbf22bf7b,0x3f46be48,
0xbf46bf6d,0x3f22bec4,0x3f7f3ec4,0x3dc93f6d,0x3f753e48,0x3e953f7b,0xbef13f0e,0xbf62bf55,0x3ec43f80,0xbf6d0000,0xbec4bf80,0x3f6d0000,
0xbf6dbf35,0x3ec4bf35,0x3f6d3f35,0xbec43f35,0x3f6d0000,0x3ec43f80,0xbf6d0000,0xbec4bf80,0xbec43f35,0xbf6dbf35,0x3ec4bf35,0x3f6d3f35,
0xbf750000,0xbe95bf80,0x3f623f35,0xbef13f35,0x3f22bf0e,0x3f463f55,0xbf7fbe48,0xbdc9bf7b,0xbdc93f6d,0xbf7fbec4,0x3f46bec4,0x3f223f6d,
0xbef1bf7b,0x3f62be48,0xbe953f55,0xbf75bf0e,0xbe48bf80,0x3f7b0000,0xbf7b0000,0xbe48bf80,0x3f0e3f6d,0xbf553ec4,0x3f55bec4,0x3f0e3f6d,
0xbf55bf35,0x3f0ebf35,0xbf0e3f35,0xbf55bf35,0x3f7b3ec4,0xbe483f6d,0x3e48bf6d,0x3f7b3ec4,0x3f7f0000,0x3dc93f80,0x3f22bf35,0x3f463f35,
0xbf753e48,0xbe95bf7b,0xbef13f55,0xbf62bf0e,0x3f62bec4,0x3ef13f6d,0x3e95bf6d,0x3f753ec4,0xbf463f0e,0xbf22bf55,0xbdc93f7b,0xbf7fbe48,
0x3f80,0xbf800000,0x3f80,0xbf800000,0xbf80,0x3f800000,0xbf80,0x3f800000,0x3f80,0xbf800000,0x3f80,0xbf800000,
0xbf80,0x3f800000,0xbf80,0x3f800000,0xbf7f0000,0x3dc9bf80,0xbf22bf35,0x3f46bf35,0x3f753e48,0xbe953f7b,0x3ef13f55,0xbf623f0e,
0xbf62bec4,0x3ef1bf6d,0xbe95bf6d,0x3f75bec4,0x3f463f0e,0xbf223f55,0x3dc93f7b,0xbf7f3e48,0x3e48bf80,0x3f7b0000,0x3f7b0000,0xbe483f80,
0xbf0e3f6d,0xbf55bec4,0xbf55bec4,0x3f0ebf6d,0x3f55bf35,0x3f0e3f35,0x3f0e3f35,0xbf553f35,0xbf7b3ec4,0xbe48bf6d,0xbe48bf6d,0x3f7bbec4,
0x3f750000,0xbe953f80,0xbf623f35,0xbef1bf35,0xbf22bf0e,0x3f46bf55,0x3f7fbe48,0xbdc93f7b,0x3dc93f6d,0xbf7f3ec4,0xbf46bec4,0x3f22bf6d,
0x3ef1bf7b,0x3f623e48,0x3e953f55,0xbf753f0e,0xbec43f80,0xbf6d0000,0x3ec4bf80,0x3f6d0000,0x3f6dbf35,0x3ec43f35,0xbf6d3f35,0xbec4bf35,
0xbf6d0000,0x3ec4bf80,0x3f6d0000,0xbec43f80,0x3ec43f35,0xbf6d3f35,0xbec4bf35,0x3f6dbf35,0xbf620000,0x3ef1bf80,0x3e953f35,0xbf753f35,
0x3dc93f55,0xbf7f3f0e,0x3f22bf7b,0x3f463e48,0x3f46bf6d,0x3f223ec4,0xbf7f3ec4,0x3dc9bf6d,0xbf753e48,0x3e95bf7b,0x3ef13f0e,0xbf623f55,
0x3f0ebf80,0x3f550000,0xbf550000,0x3f0ebf80,0xbf7b3ec4,0x3e48bf6d,0xbe483f6d,0xbf7b3ec4,0x3e483f35,0xbf7b3f35,0x3f7bbf35,0x3e483f35,
0x3f55bf6d,0x3f0e3ec4,0xbf0ebec4,0x3f55bf6d,0x3f460000,0xbf223f80,0x3f7fbf35,0x3dc93f35,0x3ef1bf7b,0x3f62be48,0xbe95bf0e,0x3f75bf55,
0xbf753ec4,0x3e95bf6d,0xbf623f6d,0xbef1bec4,0xbdc93f55,0xbf7f3f0e,0x3f223e48,0xbf463f7b,0xbf353f80,0xbf350000,0xbf353f80,0xbf350000,
0x3f350000,0xbf353f80,0x3f350000,0xbf353f80,0x3f35bf80,0x3f350000,0x3f35bf80,0x3f350000,0xbf350000,0x3f35bf80,0xbf350000,0x3f35bf80,
0xbf220000,0x3f46bf80,0x3dc9bf35,0x3f7fbf35,0xbf623f7b,0xbef1be48,0xbf753f0e,0x3e95bf55,0x3e953ec4,0xbf753f6d,0xbef13f6d,0xbf623ec4,
0x3f7fbf55,0x3dc93f0e,0x3f46be48,0xbf223f7b,0x3f55bf80,0x3f0e0000,0x3f0e0000,0xbf553f80,0xbe48bec4,0x3f7bbf6d,0x3f7bbf6d,0x3e483ec4,
0xbf7b3f35,0x3e48bf35,0x3e48bf35,0x3f7bbf35,0xbf0e3f6d,0xbf553ec4,0xbf553ec4,0x3f0ebf6d,0x3ef10000,0xbf623f80,0xbf753f35,0x3e95bf35,
0x3f7fbf55,0xbdc93f0e,0xbf463f7b,0xbf223e48,0x3f22bf6d,0x3f46bec4,0x3dc93ec4,0xbf7f3f6d,0xbe95be48,0x3f75bf7b,0x3f62bf0e,0xbef13f55,
0xbf6d3f80,0xbec40000,0x3f6dbf80,0x3ec40000,0xbec43f35,0xbf6d3f35,0x3ec4bf35,0x3f6dbf35,0x3ec40000,0xbf6d3f80,0xbec40000,0x3f6dbf80,
0x3f6dbf35,0xbec43f35,0xbf6d3f35,0x3ec4bf35,0xbe950000,0x3f75bf80,0xbef13f35,0xbf623f35,0xbf463f0e,0x3f22bf55,0x3dc93e48,0xbf7f3f7b,
0xbf7f3f6d,0x3dc9bec4,0x3f22bec4,0xbf463f6d,0xbf623f7b,0xbef13e48,0x3f75bf55,0xbe953f0e,0x3f7bbf80,0x3e480000,0xbe480000,0x3f7bbf80,
0x3f55bf6d,0x3f0ebec4,0xbf0e3ec4,0x3f55bf6d,0x3f0ebf35,0x3f55bf35,0xbf553f35,0x3f0ebf35,0x3e48bec4,0x3f7bbf6d,0xbf7b3f6d,0x3e48bec4,
0x3dc90000,0xbf7f3f80,0x3f46bf35,0xbf223f35,0x3e95be48,0xbf753f7b,0x3f62bf55,0xbef13f0e,0x3ef1bec4,0xbf623f6d,0x3f75bf6d,0xbe953ec4,
0x3f22bf0e,0xbf463f55,0x3f7fbf7b,0xbdc93e48,0x3f803f80,0xbf803f80,0x3f803f80,0xbf803f80,0x3f803f80,0xbf803f80,0x3f803f80,0xbf803f80,
0x3f803f80,0xbf803f80,0x3f803f80,0xbf803f80,0x3f803f80,0xbf803f80,0x3f803f80,0xbf803f80,0xbf7fbf80,0x3dc90000,0xbf22bf35,0x3f463f35,
0xbf75bf7b,0x3e953e48,0xbef1bf0e,0x3f623f55,0xbf62bf6d,0x3ef13ec4,0xbe95bec4,0x3f753f6d,0xbf46bf55,0x3f223f0e,0xbdc9be48,0x3f7f3f7b,
0x3f7b3f80,0xbe480000,0xbe480000,0xbf7bbf80,0x3f553f6d,0xbf0ebec4,0xbf0ebec4,0xbf55bf6d,0x3f0e3f35,0xbf55bf35,0xbf55bf35,0xbf0ebf35,
0x3e483ec4,0xbf7bbf6d,0xbf7bbf6d,0xbe48bec4,0xbf75bf80,0x3e950000,0x3f623f35,0x3ef13f35,0xbf22bf55,0x3f463f0e,0x3f7f3f7b,0xbdc93e48,
0xbdc9bec4,0x3f7f3f6d,0x3f463f6d,0xbf22bec4,0x3ef13e48,0x3f623f7b,0x3e953f0e,0xbf75bf55,0x3f6d3f80,0xbec40000,0xbf6dbf80,0x3ec40000,
0x3ec43f35,0xbf6dbf35,0xbec4bf35,0x3f6d3f35,0xbec40000,0xbf6dbf80,0x3ec40000,0x3f6d3f80,0xbf6dbf35,0xbec4bf35,0x3f6d3f35,0x3ec43f35,
0xbf62bf80,0x3ef10000,0x3e953f35,0xbf75bf35,0xbdc9bf0e,0x3f7f3f55,0xbf22be48,0xbf46bf7b,0x3f463ec4,0x3f223f6d,0xbf7fbf6d,0x3dc9bec4,
0x3f753f7b,0xbe953e48,0xbef1bf55,0x3f623f0e,0x3f553f80,0xbf0e0000,0x3f0e0000,0x3f553f80,0xbe483ec4,0xbf7bbf6d,0x3f7b3f6d,0xbe483ec4,
0xbf7bbf35,0xbe48bf35,0x3e483f35,0xbf7bbf35,0xbf0ebf6d,0x3f553ec4,0xbf55bec4,0xbf0ebf6d,0xbf46bf80,0x3f220000,0xbf7fbf35,0xbdc9bf35,
0x3ef1be48,0x3f623f7b,0xbe95bf55,0x3f753f0e,0x3f753f6d,0xbe953ec4,0x3f623ec4,0x3ef13f6d,0xbdc93f0e,0xbf7fbf55,0x3f223f7b,0xbf46be48,
0x3f353f80,0xbf350000,0x3f353f80,0xbf350000,0xbf350000,0xbf35bf80,0xbf350000,0xbf35bf80,0xbf35bf80,0x3f350000,0xbf35bf80,0x3f350000,
0x3f350000,0x3f353f80,0x3f350000,0x3f353f80,0xbf22bf80,0x3f460000,0x3dc9bf35,0x3f7f3f35,0x3f623e48,0x3ef13f7b,0x3f753f55,0xbe953f0e,
0x3e953f6d,0xbf75bec4,0xbef13ec4,0xbf62bf6d,0xbf7fbf0e,0xbdc9bf55,0xbf46bf7b,0x3f22be48,0x3f0e3f80,0xbf550000,0xbf550000,0xbf0ebf80,
0xbf7bbec4,0xbe48bf6d,0xbe48bf6d,0x3f7b3ec4,0x3e48bf35,0x3f7b3f35,0x3f7b3f35,0xbe483f35,0x3f553f6d,0xbf0e3ec4,0xbf0e3ec4,0xbf55bf6d,
0xbef1bf80,0x3f620000,0x3f753f35,0xbe953f35,0x3f7f3f0e,0xbdc93f55,0xbf463e48,0xbf22bf7b,0xbf223ec4,0xbf46bf6d,0xbdc9bf6d,0x3f7f3ec4,
0xbe95bf7b,0x3f753e48,0x3f623f55,0xbef13f0e,0x3ec43f80,0xbf6d0000,0xbec4bf80,0x3f6d0000,0xbf6dbf35,0x3ec4bf35,0x3f6d3f35,0xbec43f35,
0x3f6d0000,0x3ec43f80,0xbf6d0000,0xbec4bf80,0xbec43f35,0xbf6dbf35,0x3ec4bf35,0x3f6d3f35,0xbe95bf80,0x3f750000,0xbef13f35,0xbf62bf35,
0x3f463f55,0xbf223f0e,0xbdc9bf7b,0x3f7f3e48,0xbf7fbec4,0x3dc9bf6d,0x3f223f6d,0xbf463ec4,0x3f62be48,0x3ef13f7b,0xbf75bf0e,0x3e95bf55,
0x3e483f80,0xbf7b0000,0x3f7b0000,0x3e483f80,0xbf0ebf6d,0x3f55bec4,0xbf553ec4,0xbf0ebf6d,0x3f553f35,0xbf0e3f35,0x3f0ebf35,0x3f553f35,
0xbf7bbec4,0x3e48bf6d,0xbe483f6d,0xbf7bbec4,0xbdc9bf80,0x3f7f0000,0xbf46bf35,0x3f22bf35,0x3e953f7b,0xbf753e48,0x3f623f0e,0xbef13f55,
0xbef1bf6d,0x3f62bec4,0xbf75bec4,0x3e95bf6d,0x3f223f55,0xbf463f0e,0x3f7f3e48,0xbdc93f7b,0x3f80,0xbf800000,0x3f80,0xbf800000,
0xbf80,0x3f800000,0xbf80,0x3f800000,0x3f80,0xbf800000,0x3f80,0xbf800000,0xbf80,0x3f800000,0xbf80,0x3f800000,
0x3dc9bf80,0x3f7f0000,0x3f46bf35,0x3f223f35,0xbe953f7b,0xbf75be48,0xbf623f0e,0xbef1bf55,0x3ef1bf6d,0x3f623ec4,0x3f75bec4,0x3e953f6d,
0xbf223f55,0xbf46bf0e,0xbf7f3e48,0xbdc9bf7b,0xbe483f80,0xbf7b0000,0xbf7b0000,0x3e48bf80,0x3f0ebf6d,0x3f553ec4,0x3f553ec4,0xbf0e3f6d,
0xbf553f35,0xbf0ebf35,0xbf0ebf35,0x3f55bf35,0x3f7bbec4,0x3e483f6d,0x3e483f6d,0xbf7b3ec4,0x3e95bf80,0x3f750000,0x3ef13f35,0xbf623f35,
0xbf463f55,0xbf22bf0e,0x3dc9bf7b,0x3f7fbe48,0x3f7fbec4,0x3dc93f6d,0xbf223f6d,0xbf46bec4,0xbf62be48,0x3ef1bf7b,0x3f75bf0e,0x3e953f55,
0xbec43f80,0xbf6d0000,0x3ec4bf80,0x3f6d0000,0x3f6dbf35,0x3ec43f35,0xbf6d3f35,0xbec4bf35,0xbf6d0000,0x3ec4bf80,0x3f6d0000,0xbec43f80,
0x3ec43f35,0xbf6d3f35,0xbec4bf35,0x3f6dbf35,0x3ef1bf80,0x3f620000,0xbf753f35,0xbe95bf35,0xbf7f3f0e,0xbdc9bf55,0x3f463e48,0xbf223f7b,
0x3f223ec4,0xbf463f6d,0x3dc9bf6d,0x3f7fbec4,0x3e95bf7b,0x3f75be48,0xbf623f55,0xbef1bf0e,0xbf0e3f80,0xbf550000,0x3f550000,0xbf0e3f80,
0x3f7bbec4,0xbe483f6d,0x3e48bf6d,0x3f7bbec4,0xbe48bf35,0x3f7bbf35,0xbf7b3f35,0xbe48bf35,0xbf553f6d,0xbf0ebec4,0x3f0e3ec4,0xbf553f6d,
0x3f22bf80,0x3f460000,0xbdc9bf35,0x3f7fbf35,0xbf623e48,0x3ef1bf7b,0xbf753f55,0xbe95bf0e,0xbe953f6d,0xbf753ec4,0x3ef13ec4,0xbf623f6d,
0x3f7fbf0e,0xbdc93f55,0x3f46bf7b,0x3f223e48,0xbf353f80,0xbf350000,0xbf353f80,0xbf350000,0x3f350000,0xbf353f80,0x3f350000,0xbf353f80,
0x3f35bf80,0x3f350000,0x3f35bf80,0x3f350000,0xbf350000,0x3f35bf80,0xbf350000,0x3f35bf80,0x3f46bf80,0x3f220000,0x3f7fbf35,0xbdc93f35,
0xbef1be48,0x3f62bf7b,0x3e95bf55,0x3f75bf0e,0xbf753f6d,0xbe95bec4,0xbf623ec4,0x3ef1bf6d,0x3dc93f0e,0xbf7f3f55,0xbf223f7b,0xbf463e48,
0xbf553f80,0xbf0e0000,0xbf0e0000,0x3f55bf80,0x3e483ec4,0xbf7b3f6d,0xbf7b3f6d,0xbe48bec4,0x3f7bbf35,0xbe483f35,0xbe483f35,0xbf7b3f35,
0x3f0ebf6d,0x3f55bec4,0x3f55bec4,0xbf0e3f6d,0x3f62bf80,0x3ef10000,0xbe953f35,0xbf753f35,0x3dc9bf0e,0x3f7fbf55,0x3f22be48,0xbf463f7b,
0xbf463ec4,0x3f22bf6d,0x3f7fbf6d,0x3dc93ec4,0xbf753f7b,0xbe95be48,0x3ef1bf55,0x3f62bf0e,0xbf6d3f80,0xbec40000,0x3f6dbf80,0x3ec40000,
0xbec43f35,0xbf6d3f35,0x3ec4bf35,0x3f6dbf35,0x3ec40000,0xbf6d3f80,0xbec40000,0x3f6dbf80,0x3f6dbf35,0xbec43f35,0xbf6d3f35,0x3ec4bf35,
0x3f75bf80,0x3e950000,0xbf623f35,0x3ef1bf35,0x3f22bf55,0x3f46bf0e,0xbf7f3f7b,0xbdc9be48,0x3dc9bec4,0x3f7fbf6d,0xbf463f6d,0xbf223ec4,
0xbef13e48,0x3f62bf7b,0xbe953f0e,0xbf753f55,0xbf7b3f80,0xbe480000,0x3e480000,0xbf7b3f80,0xbf553f6d,0xbf0e3ec4,0x3f0ebec4,0xbf553f6d,
0xbf0e3f35,0xbf553f35,0x3f55bf35,0xbf0e3f35,0xbe483ec4,0xbf7b3f6d,0x3f7bbf6d,0xbe483ec4,0x3f7fbf80,0x3dc90000,0x3f22bf35,0x3f46bf35,
0x3f75bf7b,0x3e95be48,0x3ef1bf0e,0x3f62bf55,0x3f62bf6d,0x3ef1bec4,0x3e95bec4,0x3f75bf6d,0x3f46bf55,0x3f22bf0e,0x3dc9be48,0x3f7fbf7b,
0x3f803f80,0xbf803f80,0x3f803f80,0xbf803f80,0x3f803f80,0xbf803f80,0x3f803f80,0xbf803f80,0x3f803f80,0xbf803f80,0x3f803f80,0xbf803f80,
0x3f803f80,0xbf803f80,0x3f803f80,0xbf803f80,0x3dc90000,0x3f7f3f80,0x3f463f35,0x3f223f35,0x3e953e48,0x3f753f7b,0x3f623f55,0x3ef13f0e,
0x3ef13ec4,0x3f623f6d,0x3f753f6d,0x3e953ec4,0x3f223f0e,0x3f463f55,0x3f7f3f7b,0x3dc93e48,0xbf7bbf80,0x3e480000,0x3e480000,0x3f7b3f80,
0xbf55bf6d,0x3f0e3ec4,0x3f0e3ec4,0x3f553f6d,0xbf0ebf35,0x3f553f35,0x3f553f35,0x3f0e3f35,0xbe48bec4,0x3f7b3f6d,0x3f7b3f6d,0x3e483ec4,
0xbe950000,0xbf75bf80,0xbef1bf35,0x3f623f35,0xbf46bf0e,0xbf22bf55,0x3dc9be48,0x3f7f3f7b,0xbf7fbf6d,0xbdc9bec4,0x3f223ec4,0x3f463f6d,
0xbf62bf7b,0x3ef13e48,0x3f753f55,0x3e953f0e,0x3f6d3f80,0xbec40000,0xbf6dbf80,0x3ec40000,0x3ec43f35,0xbf6dbf35,0xbec4bf35,0x3f6d3f35,
0xbec40000,0xbf6dbf80,0x3ec40000,0x3f6d3f80,0xbf6dbf35,0xbec4bf35,0x3f6d3f35,0x3ec43f35,0x3ef10000,0x3f623f80,0xbf75bf35,0xbe95bf35,
0x3f7f3f55,0x3dc93f0e,0xbf46bf7b,0x3f223e48,0x3f223f6d,0xbf46bec4,0x3dc9bec4,0x3f7f3f6d,0xbe953e48,0xbf75bf7b,0x3f623f0e,0x3ef13f55,
0xbf55bf80,0x3f0e0000,0xbf0e0000,0xbf55bf80,0x3e48bec4,0x3f7b3f6d,0xbf7bbf6d,0x3e48bec4,0x3f7b3f35,0x3e483f35,0xbe48bf35,0x3f7b3f35,
0x3f0e3f6d,0xbf55bec4,0x3f553ec4,0x3f0e3f6d,0xbf220000,0xbf46bf80,0x3dc93f35,0xbf7fbf35,0xbf62bf7b,0x3ef1be48,0xbf75bf0e,0xbe95bf55,
0x3e95bec4,0x3f753f6d,0xbef1bf6d,0x3f623ec4,0x3f7f3f55,0xbdc93f0e,0x3f463e48,0x3f223f7b,0x3f353f80,0xbf350000,0x3f353f80,0xbf350000,
0xbf350000,0xbf35bf80,0xbf350000,0xbf35bf80,0xbf35bf80,0x3f350000,0xbf35bf80,0x3f350000,0x3f350000,0x3f353f80,0x3f350000,0x3f353f80,
0x3f460000,0x3f223f80,0x3f7f3f35,0xbdc93f35,0x3ef13f7b,0xbf62be48,0xbe953f0e,0xbf75bf55,0xbf75bec4,0xbe95bf6d,0xbf62bf6d,0x3ef1bec4,
0xbdc9bf55,0x3f7f3f0e,0x3f22be48,0x3f463f7b,0xbf0ebf80,0x3f550000,0x3f550000,0x3f0e3f80,0x3f7b3ec4,0x3e483f6d,0x3e483f6d,0xbf7bbec4,
0xbe483f35,0xbf7bbf35,0xbf7bbf35,0x3e48bf35,0xbf55bf6d,0x3f0ebec4,0x3f0ebec4,0x3f553f6d,0xbf620000,0xbef1bf80,0x3e95bf35,0x3f753f35,
0x3dc9bf55,0x3f7f3f0e,0x3f223f7b,0xbf463e48,0x3f463f6d,0xbf223ec4,0xbf7fbec4,0xbdc9bf6d,0xbf75be48,0xbe95bf7b,0x3ef1bf0e,0x3f623f55,
0x3ec43f80,0xbf6d0000,0xbec4bf80,0x3f6d0000,0xbf6dbf35,0x3ec4bf35,0x3f6d3f35,0xbec43f35,0x3f6d0000,0x3ec43f80,0xbf6d0000,0xbec4bf80,
0xbec43f35,0xbf6dbf35,0x3ec4bf35,0x3f6d3f35,0x3f750000,0x3e953f80,0xbf62bf35,0x3ef1bf35,0xbf223f0e,0xbf46bf55,0x3f7f3e48,0x3dc93f7b,
0x3dc9bf6d,0x3f7f3ec4,0xbf463ec4,0xbf22bf6d,0x3ef13f7b,0xbf623e48,0x3e95bf55,0x3f753f0e,0xbe48bf80,0x3f7b0000,0xbf7b0000,0xbe48bf80,
0x3f0e3f6d,0xbf553ec4,0x3f55bec4,0x3f0e3f6d,0xbf55bf35,0x3f0ebf35,0xbf0e3f35,0xbf55bf35,0x3f7b3ec4,0xbe483f6d,0x3e48bf6d,0x3f7b3ec4,
0xbf7f0000,0xbdc9bf80,0xbf223f35,0xbf46bf35,0x3f75be48,0x3e953f7b,0x3ef1bf55,0x3f623f0e,0xbf623ec4,0xbef1bf6d,0xbe953f6d,0xbf75bec4,
0x3f46bf0e,0x3f223f55,0x3dc9bf7b,0x3f7f3e48,0x3f80,0xbf800000,0x3f80,0xbf800000,0xbf80,0x3f800000,0xbf80,0x3f800000,
0x3f80,0xbf800000,0x3f80,0xbf800000,0xbf80,0x3f800000,0xbf80,0x3f800000,0x3f7f0000,0xbdc93f80,0x3f223f35,0xbf463f35,
0xbf75be48,0x3e95bf7b,0xbef1bf55,0x3f62bf0e,0x3f623ec4,0xbef13f6d,0x3e953f6d,0xbf753ec4,0xbf46bf0e,0x3f22bf55,0xbdc9bf7b,0x3f7fbe48,
0x3e48bf80,0x3f7b0000,0x3f7b0000,0xbe483f80,0xbf0e3f6d,0xbf55bec4,0xbf55bec4,0x3f0ebf6d,0x3f55bf35,0x3f0e3f35,0x3f0e3f35,0xbf553f35,
0xbf7b3ec4,0xbe48bf6d,0xbe48bf6d,0x3f7bbec4,0xbf750000,0x3e95bf80,0x3f62bf35,0x3ef13f35,0x3f223f0e,0xbf463f55,0xbf7f3e48,0x3dc9bf7b,
0xbdc9bf6d,0x3f7fbec4,0x3f463ec4,0xbf223f6d,0xbef13f7b,0xbf62be48,0xbe95bf55,0x3f75bf0e,0xbec43f80,0xbf6d0000,0x3ec4bf80,0x3f6d0000,
0x3f6dbf35,0x3ec43f35,0xbf6d3f35,0xbec4bf35,0xbf6d0000,0x3ec4bf80,0x3f6d0000,0xbec43f80,0x3ec43f35,0xbf6d3f35,0xbec4bf35,0x3f6dbf35,
0x3f620000,0xbef13f80,0xbe95bf35,0x3f75bf35,0xbdc9bf55,0x3f7fbf0e,0xbf223f7b,0xbf46be48,0xbf463f6d,0xbf22bec4,0x3f7fbec4,0xbdc93f6d,
0x3f75be48,0xbe953f7b,0xbef1bf0e,0x3f62bf55,0x3f0ebf80,0x3f550000,0xbf550000,0x3f0ebf80,0xbf7b3ec4,0x3e48bf6d,0xbe483f6d,0xbf7b3ec4,
0x3e483f35,0xbf7b3f35,0x3f7bbf35,0x3e483f35,0x3f55bf6d,0x3f0e3ec4,0xbf0ebec4,0x3f55bf6d,0xbf460000,0x3f22bf80,0xbf7f3f35,0xbdc9bf35,
0xbef13f7b,0xbf623e48,0x3e953f0e,0xbf753f55,0x3f75bec4,0xbe953f6d,0x3f62bf6d,0x3ef13ec4,0x3dc9bf55,0x3f7fbf0e,0xbf22be48,0x3f46bf7b,
0xbf353f80,0xbf350000,0xbf353f80,0xbf350000,0x3f350000,0xbf353f80,0x3f350000,0xbf353f80,0x3f35bf80,0x3f350000,0x3f35bf80,0x3f350000,
0xbf350000,0x3f35bf80,0xbf350000,0x3f35bf80,0x3f220000,0xbf463f80,0xbdc93f35,0xbf7f3f35,0x3f62bf7b,0x3ef13e48,0x3f75bf0e,0xbe953f55,
0xbe95bec4,0x3f75bf6d,0x3ef1bf6d,0x3f62bec4,0xbf7f3f55,0xbdc9bf0e,0xbf463e48,0x3f22bf7b,0x3f55bf80,0x3f0e0000,0x3f0e0000,0xbf553f80,
0xbe48bec4,0x3f7bbf6d,0x3f7bbf6d,0x3e483ec4,0xbf7b3f35,0x3e48bf35,0x3e48bf35,0x3f7bbf35,0xbf0e3f6d,0xbf553ec4,0xbf553ec4,0x3f0ebf6d,
0xbef10000,0x3f62bf80,0x3f75bf35,0xbe953f35,0xbf7f3f55,0x3dc9bf0e,0x3f46bf7b,0x3f22be48,0xbf223f6d,0xbf463ec4,0xbdc9bec4,0x3f7fbf6d,
0x3e953e48,0xbf753f7b,0xbf623f0e,0x3ef1bf55,0xbf6d3f80,0xbec40000,0x3f6dbf80,0x3ec40000,0xbec43f35,0xbf6d3f35,0x3ec4bf35,0x3f6dbf35,
0x3ec40000,0xbf6d3f80,0xbec40000,0x3f6dbf80,0x3f6dbf35,0xbec43f35,0xbf6d3f35,0x3ec4bf35,0x3e950000,0xbf753f80,0x3ef1bf35,0x3f62bf35,
0x3f46bf0e,0xbf223f55,0xbdc9be48,0x3f7fbf7b,0x3f7fbf6d,0xbdc93ec4,0xbf223ec4,0x3f46bf6d,0x3f62bf7b,0x3ef1be48,0xbf753f55,0x3e95bf0e,
0x3f7bbf80,0x3e480000,0xbe480000,0x3f7bbf80,0x3f55bf6d,0x3f0ebec4,0xbf0e3ec4,0x3f55bf6d,0x3f0ebf35,0x3f55bf35,0xbf553f35,0x3f0ebf35,
0x3e48bec4,0x3f7bbf6d,0xbf7b3f6d,0x3e48bec4,0xbdc90000,0x3f7fbf80,0xbf463f35,0x3f22bf35,0xbe953e48,0x3f75bf7b,0xbf623f55,0x3ef1bf0e,
0xbef13ec4,0x3f62bf6d,0xbf753f6d,0x3e95bec4,0xbf223f0e,0x3f46bf55,0xbf7f3f7b,0x3dc9be48,0x40003f80,0x3fb53f80,0x3f80,0xbfb53f80,
0x40004000,0xbfb50000,0x0,0xbfb5c000,0x40004000,0xbfb5c000,0x0,0x3fb50000,0x40004000,0x3fb50000,0x0,0x3fb54000,
0x3fff3f80,0x3fa23f80,0xbe49bf80,0xbfc6bf80,0x3ff53ffb,0xbfe2bec8,0xbf15bec8,0xbf71bffb,0x3fe23fed,0xbf15bfed,0xbf71bf44,0x3ff53f44,
0x3fc63fd5,0x3fff3f8e,0xbfa2bf8e,0x3e493fd5,0x3ffb3f80,0x3f8e3f80,0xbec83f80,0xbfd53f80,0x3fd53fed,0xbffbbf44,0xbf8ebf44,0xbec8bfed,
0x3f8e3fb5,0x3ec8bfb5,0xbfd5bfb5,0x3ffb3fb5,0x3ec83f44,0x3fd53fed,0xbffbbfed,0xbf8e3f44,0x3ff53f80,0x3f713f80,0xbf15bf80,0xbfe2bf80,
0x3fa23fd5,0xbfffbf8e,0xbfc6bf8e,0x3e49bfd5,0x3e493f44,0x3fa2bf44,0xbfffbfed,0x3fc63fed,0xbf71bec8,0x3f153ffb,0xbfe2bffb,0xbff5bec8,
0x3fed3f80,0x3f443f80,0xbf443f80,0xbfed3f80,0x3f443fb5,0xbfedbfb5,0xbfedbfb5,0x3f44bfb5,0xbf440000,0x3fed0000,0xbfedc000,0x3f444000,
0xbfedbfb5,0xbf443fb5,0xbf44bfb5,0xbfedbfb5,0x3fe23f80,0x3f153f80,0xbf71bf80,0xbff5bf80,0x3e493f8e,0xbfc6bfd5,0xbfffbfd5,0x3fa2bf8e,
0xbfc6bf44,0x3fff3f44,0xbfa2bfed,0xbe493fed,0xbff5bffb,0xbfe23ec8,0x3f15bec8,0xbf71bffb,0x3fd53f80,0x3ec83f80,0xbf8e3f80,0xbffb3f80,
0xbec83f44,0xbf8ebfed,0xbffbbfed,0x3fd5bf44,0xbffbbfb5,0x3fd53fb5,0xbec8bfb5,0xbf8e3fb5,0xbf8ebfed,0xbffbbf44,0x3fd53f44,0x3ec8bfed,
0x3fc63f80,0x3e493f80,0xbfa2bf80,0xbfffbf80,0xbf713ec8,0xbf15bffb,0xbfe2bffb,0x3ff5bec8,0xbff5bfed,0x3f713fed,0x3f15bf44,0xbfe23f44,
0x3e49bf8e,0xbfa2bfd5,0x3fff3fd5,0x3fc6bf8e,0x3f80,0xbfb53f80,0xc0003f80,0xbfb53f80,0xc000,0x3fb50000,0x40000000,0xbfb54000,
0x4000,0x3fb5c000,0xc0000000,0x3fb50000,0xc000,0xbfb50000,0x40000000,0x3fb5c000,0xbe493f80,0xbfc63f80,0xbfffbf80,0xbfa2bf80,
0x3f15bffb,0x3f713ec8,0x3ff53ec8,0xbfe23ffb,0xbf713fed,0x3ff5bfed,0xbfe2bf44,0x3f153f44,0x3fa2bfd5,0xbe49bf8e,0x3fc63f8e,0x3fffbfd5,
0xbec83f80,0xbfd53f80,0xbffb3f80,0xbf8e3f80,0x3f8ebfed,0x3ec83f44,0x3fd53f44,0xbffb3fed,0xbfd53fb5,0x3ffbbfb5,0xbf8ebfb5,0xbec83fb5,
0x3ffbbf44,0x3f8ebfed,0x3ec83fed,0x3fd5bf44,0xbf153f80,0xbfe23f80,0xbff5bf80,0xbf71bf80,0x3fc6bfd5,0xbe493f8e,0x3fa23f8e,0xbfff3fd5,
0xbfff3f44,0x3fc6bf44,0xbe49bfed,0xbfa23fed,0x3fe23ec8,0x3ff5bffb,0xbf713ffb,0x3f153ec8,0xbf443f80,0xbfed3f80,0xbfed3f80,0xbf443f80,
0x3fedbfb5,0xbf443fb5,0x3f443fb5,0xbfed3fb5,0xbfed0000,0x3f440000,0x3f44c000,0xbfed4000,0x3f443fb5,0x3fedbfb5,0xbfed3fb5,0xbf443fb5,
0xbf713f80,0xbff53f80,0xbfe2bf80,0xbf15bf80,0x3fffbf8e,0xbfa23fd5,0x3e493fd5,0xbfc63f8e,0xbfa2bf44,0xbe493f44,0x3fc6bfed,0xbfff3fed,
0xbf153ffb,0x3f71bec8,0xbff53ec8,0xbfe23ffb,0xbf8e3f80,0xbffb3f80,0xbfd53f80,0xbec83f80,0x3ffbbf44,0xbfd53fed,0xbec83fed,0xbf8e3f44,
0xbec8bfb5,0xbf8e3fb5,0x3ffbbfb5,0xbfd53fb5,0xbfd53fed,0xbec83f44,0xbf8ebf44,0xbffb3fed,0xbfa23f80,0xbfff3f80,0xbfc6bf80,0xbe49bf80,
0x3fe2bec8,0xbff53ffb,0xbf713ffb,0xbf153ec8,0x3f15bfed,0xbfe23fed,0x3ff5bf44,0xbf713f44,0xbfff3f8e,0xbfc63fd5,0x3e49bfd5,0xbfa23f8e,
0xc0003f80,0xbfb53f80,0x3f80,0x3fb53f80,0xc0004000,0x3fb50000,0x0,0x3fb5c000,0xc0004000,0x3fb5c000,0x0,0xbfb50000,
0xc0004000,0xbfb50000,0x0,0xbfb54000,0xbfff3f80,0xbfa23f80,0x3e49bf80,0x3fc6bf80,0xbff53ffb,0x3fe2bec8,0x3f15bec8,0x3f71bffb,
0xbfe23fed,0x3f15bfed,0x3f71bf44,0xbff53f44,0xbfc63fd5,0xbfff3f8e,0x3fa2bf8e,0xbe493fd5,0xbffb3f80,0xbf8e3f80,0x3ec83f80,0x3fd53f80,
0xbfd53fed,0x3ffbbf44,0x3f8ebf44,0x3ec8bfed,0xbf8e3fb5,0xbec8bfb5,0x3fd5bfb5,0xbffb3fb5,0xbec83f44,0xbfd53fed,0x3ffbbfed,0x3f8e3f44,
0xbff53f80,0xbf713f80,0x3f15bf80,0x3fe2bf80,0xbfa23fd5,0x3fffbf8e,0x3fc6bf8e,0xbe49bfd5,0xbe493f44,0xbfa2bf44,0x3fffbfed,0xbfc63fed,
0x3f71bec8,0xbf153ffb,0x3fe2bffb,0x3ff5bec8,0xbfed3f80,0xbf443f80,0x3f443f80,0x3fed3f80,0xbf443fb5,0x3fedbfb5,0x3fedbfb5,0xbf44bfb5,
0x3f440000,0xbfed0000,0x3fedc000,0xbf444000,0x3fedbfb5,0x3f443fb5,0x3f44bfb5,0x3fedbfb5,0xbfe23f80,0xbf153f80,0x3f71bf80,0x3ff5bf80,
0xbe493f8e,0x3fc6bfd5,0x3fffbfd5,0xbfa2bf8e,0x3fc6bf44,0xbfff3f44,0x3fa2bfed,0x3e493fed,0x3ff5bffb,0x3fe23ec8,0xbf15bec8,0x3f71bffb,
0xbfd53f80,0xbec83f80,0x3f8e3f80,0x3ffb3f80,0x3ec83f44,0x3f8ebfed,0x3ffbbfed,0xbfd5bf44,0x3ffbbfb5,0xbfd53fb5,0x3ec8bfb5,0x3f8e3fb5,
0x3f8ebfed,0x3ffbbf44,0xbfd53f44,0xbec8bfed,0xbfc63f80,0xbe493f80,0x3fa2bf80,0x3fffbf80,0x3f713ec8,0x3f15bffb,0x3fe2bffb,0xbff5bec8,
0x3ff5bfed,0xbf713fed,0xbf15bf44,0x3fe23f44,0xbe49bf8e,0x3fa2bfd5,0xbfff3fd5,0xbfc6bf8e,0x3f80,0x3fb53f80,0x40003f80,0x3fb53f80,
0xc000,0xbfb50000,0xc0000000,0x3fb54000,0x4000,0xbfb5c000,0x40000000,0xbfb50000,0xc000,0x3fb50000,0xc0000000,0xbfb5c000,
0x3e493f80,0x3fc63f80,0x3fffbf80,0x3fa2bf80,0xbf15bffb,0xbf713ec8,0xbff53ec8,0x3fe23ffb,0x3f713fed,0xbff5bfed,0x3fe2bf44,0xbf153f44,
0xbfa2bfd5,0x3e49bf8e,0xbfc63f8e,0xbfffbfd5,0x3ec83f80,0x3fd53f80,0x3ffb3f80,0x3f8e3f80,0xbf8ebfed,0xbec83f44,0xbfd53f44,0x3ffb3fed,
0x3fd53fb5,0xbffbbfb5,0x3f8ebfb5,0x3ec83fb5,0xbffbbf44,0xbf8ebfed,0xbec83fed,0xbfd5bf44,0x3f153f80,0x3fe23f80,0x3ff5bf80,0x3f71bf80,
0xbfc6bfd5,0x3e493f8e,0xbfa23f8e,0x3fff3fd5,0x3fff3f44,0xbfc6bf44,0x3e49bfed,0x3fa23fed,0xbfe23ec8,0xbff5bffb,0x3f713ffb,0xbf153ec8,
0x3f443f80,0x3fed3f80,0x3fed3f80,0x3f443f80,0xbfedbfb5,0x3f443fb5,0xbf443fb5,0x3fed3fb5,0x3fed0000,0xbf440000,0xbf44c000,0x3fed4000,
0xbf443fb5,0xbfedbfb5,0x3fed3fb5,0x3f443fb5,0x3f713f80,0x3ff53f80,0x3fe2bf80,0x3f15bf80,0xbfffbf8e,0x3fa23fd5,0xbe493fd5,0x3fc63f8e,
0x3fa2bf44,0x3e493f44,0xbfc6bfed,0x3fff3fed,0x3f153ffb,0xbf71bec8,0x3ff53ec8,0x3fe23ffb,0x3f8e3f80,0x3ffb3f80,0x3fd53f80,0x3ec83f80,
0xbffbbf44,0x3fd53fed,0x3ec83fed,0x3f8e3f44,0x3ec8bfb5,0x3f8e3fb5,0xbffbbfb5,0x3fd53fb5,0x3fd53fed,0x3ec83f44,0x3f8ebf44,0x3ffb3fed,
0x3fa23f80,0x3fff3f80,0x3fc6bf80,0x3e49bf80,0xbfe2bec8,0x3ff53ffb,0x3f713ffb,0x3f153ec8,0xbf15bfed,0x3fe23fed,0xbff5bf44,0x3f713f44,
0x3fff3f8e,0x3fc63fd5,0xbe49bfd5,0x3fa23f8e,0x40004000,0x3fb54000,0x0,0xbfb50000,0x40004000,0xbfb50000,0x0,0xbfb5c000,
0x40004000,0xbfb5c000,0x0,0x3fb50000,0x40004000,0x3fb50000,0x0,0x3fb54000,0x3fa23fb5,0xbe493fb5,0xbfc6bfb5,0xbfffbfb5,
0x3f713f8e,0xbff5bfd5,0xbfe2bfd5,0x3f15bf8e,0x3f153f44,0x3f71bf44,0xbff5bfed,0x3fe23fed,0x3e493ec8,0x3fc63ffb,0xbfffbffb,0xbfa23ec8,
0xbec80000,0xbfd50000,0xbffbc000,0xbf8ec000,0xbf8ebf44,0xbec8bfed,0xbfd5bfed,0x3ffb3f44,0xbfd5bfb5,0x3ffb3fb5,0xbf8ebfb5,0xbec83fb5,
0xbffbbfed,0xbf8e3f44,0xbec8bf44,0xbfd5bfed,0xbfe2bfb5,0xbff5bfb5,0xbf71bfb5,0x3f15bfb5,0xbfffbffb,0x3fc6bec8,0x3e49bec8,0x3fa23ffb,
0xbfc6bfed,0x3e493fed,0x3fa23f44,0xbfffbf44,0xbf15bf8e,0xbfe2bfd5,0x3ff53fd5,0x3f71bf8e,0xbfedc000,0xbf44c000,0x3f440000,0x3fed0000,
0xbf44bfb5,0x3fed3fb5,0x3fed3fb5,0xbf443fb5,0x3f440000,0xbfed0000,0x3fed4000,0xbf44c000,0x3fed3fb5,0x3f44bfb5,0x3f443fb5,0x3fed3fb5,
0xbf15bfb5,0x3f71bfb5,0x3ff53fb5,0x3fe23fb5,0x3fa23ec8,0x3e493ffb,0x3fc63ffb,0xbfffbec8,0x3fff3fed,0xbfa2bfed,0xbe493f44,0x3fc6bf44,
0x3f713fd5,0x3ff53f8e,0xbfe2bf8e,0xbf153fd5,0x3f8e0000,0x3ffb0000,0x3fd54000,0x3ec84000,0x3ffb3fed,0xbfd53f44,0xbec83f44,0xbf8ebfed,
0x3ec83fb5,0x3f8ebfb5,0xbffbbfb5,0x3fd53fb5,0xbfd5bf44,0xbec83fed,0xbf8ebfed,0xbffbbf44,0x3fff3fb5,0x3fc63fb5,0x3e493fb5,0xbfa23fb5,
0x3f153fd5,0xbfe2bf8e,0xbff5bf8e,0x3f71bfd5,0xbfe2bf44,0x3ff53f44,0xbf71bfed,0xbf153fed,0xbfa2bffb,0xbfffbec8,0x3fc63ec8,0x3e49bffb,
0x4000,0xbfb54000,0xc0000000,0xbfb50000,0xc000,0x3fb50000,0x40000000,0xbfb54000,0x4000,0x3fb5c000,0xc0000000,0x3fb50000,
0xc000,0xbfb50000,0x40000000,0x3fb5c000,0xbfc63fb5,0xbfff3fb5,0xbfa2bfb5,0x3e49bfb5,0x3fe2bf8e,0xbf153fd5,0x3f713fd5,0xbff53f8e,
0xbff53f44,0x3fe2bf44,0xbf15bfed,0xbf713fed,0x3fffbec8,0x3fa2bffb,0x3e493ffb,0x3fc6bec8,0xbffb0000,0xbf8e0000,0x3ec8c000,0x3fd5c000,
0x3fd53f44,0xbffb3fed,0xbf8e3fed,0xbec8bf44,0xbf8ebfb5,0xbec83fb5,0x3fd5bfb5,0xbffb3fb5,0x3ec83fed,0x3fd5bf44,0xbffb3f44,0xbf8e3fed,
0xbf71bfb5,0x3f15bfb5,0x3fe2bfb5,0x3ff5bfb5,0xbe493ffb,0xbfa23ec8,0xbfff3ec8,0x3fc6bffb,0x3fa2bfed,0xbfff3fed,0x3fc63f44,0xbe49bf44,
0xbff53f8e,0xbf713fd5,0xbf15bfd5,0xbfe23f8e,0x3f44c000,0x3fedc000,0x3fed0000,0x3f440000,0xbfed3fb5,0x3f44bfb5,0xbf44bfb5,0x3fedbfb5,
0x3fed0000,0xbf440000,0xbf444000,0x3fedc000,0xbf44bfb5,0xbfed3fb5,0x3fedbfb5,0x3f44bfb5,0x3ff5bfb5,0x3fe2bfb5,0x3f153fb5,0xbf713fb5,
0xbfc6bec8,0x3fffbffb,0x3fa2bffb,0x3e493ec8,0xbe493fed,0x3fc6bfed,0xbfff3f44,0x3fa2bf44,0x3fe2bfd5,0x3f15bf8e,0x3f713f8e,0x3ff5bfd5,
0x3fd50000,0x3ec80000,0xbf8e4000,0xbffb4000,0x3ec8bfed,0x3f8ebf44,0x3ffbbf44,0xbfd53fed,0xbffb3fb5,0x3fd5bfb5,0xbec8bfb5,0xbf8e3fb5,
0x3f8e3f44,0x3ffbbfed,0xbfd53fed,0xbec83f44,0x3e493fb5,0xbfa23fb5,0xbfff3fb5,0xbfc63fb5,0x3ff5bfd5,0xbf713f8e,0x3f153f8e,0xbfe23fd5,
0xbf71bf44,0xbf153f44,0x3fe2bfed,0xbff53fed,0xbfc63ffb,0xbe493ec8,0xbfa2bec8,0xbfff3ffb,0xc0004000,0xbfb54000,0x0,0x3fb50000,
0xc0004000,0x3fb50000,0x0,0x3fb5c000,0xc0004000,0x3fb5c000,0x0,0xbfb50000,0xc0004000,0xbfb50000,0x0,0xbfb54000,
0xbfa23fb5,0x3e493fb5,0x3fc6bfb5,0x3fffbfb5,0xbf713f8e,0x3ff5bfd5,0x3fe2bfd5,0xbf15bf8e,0xbf153f44,0xbf71bf44,0x3ff5bfed,0xbfe23fed,
0xbe493ec8,0xbfc63ffb,0x3fffbffb,0x3fa23ec8,0x3ec80000,0x3fd50000,0x3ffbc000,0x3f8ec000,0x3f8ebf44,0x3ec8bfed,0x3fd5bfed,0xbffb3f44,
0x3fd5bfb5,0xbffb3fb5,0x3f8ebfb5,0x3ec83fb5,0x3ffbbfed,0x3f8e3f44,0x3ec8bf44,0x3fd5bfed,0x3fe2bfb5,0x3ff5bfb5,0x3f71bfb5,0xbf15bfb5,
0x3fffbffb,0xbfc6bec8,0xbe49bec8,0xbfa23ffb,0x3fc6bfed,0xbe493fed,0xbfa23f44,0x3fffbf44,0x3f15bf8e,0x3fe2bfd5,0xbff53fd5,0xbf71bf8e,
0x3fedc000,0x3f44c000,0xbf440000,0xbfed0000,0x3f44bfb5,0xbfed3fb5,0xbfed3fb5,0x3f443fb5,0xbf440000,0x3fed0000,0xbfed4000,0x3f44c000,
0xbfed3fb5,0xbf44bfb5,0xbf443fb5,0xbfed3fb5,0x3f15bfb5,0xbf71bfb5,0xbff53fb5,0xbfe23fb5,0xbfa23ec8,0xbe493ffb,0xbfc63ffb,0x3fffbec8,
0xbfff3fed,0x3fa2bfed,0x3e493f44,0xbfc6bf44,0xbf713fd5,0xbff53f8e,0x3fe2bf8e,0x3f153fd5,0xbf8e0000,0xbffb0000,0xbfd54000,0xbec84000,
0xbffb3fed,0x3fd53f44,0x3ec83f44,0x3f8ebfed,0xbec83fb5,0xbf8ebfb5,0x3ffbbfb5,0xbfd53fb5,0x3fd5bf44,0x3ec83fed,0x3f8ebfed,0x3ffbbf44,
0xbfff3fb5,0xbfc63fb5,0xbe493fb5,0x3fa23fb5,0xbf153fd5,0x3fe2bf8e,0x3ff5bf8e,0xbf71bfd5,0x3fe2bf44,0xbff53f44,0x3f71bfed,0x3f153fed,
0x3fa2bffb,0x3fffbec8,0xbfc63ec8,0xbe49bffb,0x4000,0x3fb54000,0x40000000,0x3fb50000,0xc000,0xbfb50000,0xc0000000,0x3fb54000,
0x4000,0xbfb5c000,0x40000000,0xbfb50000,0xc000,0x3fb50000,0xc0000000,0xbfb5c000,0x3fc63fb5,0x3fff3fb5,0x3fa2bfb5,0xbe49bfb5,
0xbfe2bf8e,0x3f153fd5,0xbf713fd5,0x3ff53f8e,0x3ff53f44,0xbfe2bf44,0x3f15bfed,0x3f713fed,0xbfffbec8,0xbfa2bffb,0xbe493ffb,0xbfc6bec8,
0x3ffb0000,0x3f8e0000,0xbec8c000,0xbfd5c000,0xbfd53f44,0x3ffb3fed,0x3f8e3fed,0x3ec8bf44,0x3f8ebfb5,0x3ec83fb5,0xbfd5bfb5,0x3ffb3fb5,
0xbec83fed,0xbfd5bf44,0x3ffb3f44,0x3f8e3fed,0x3f71bfb5,0xbf15bfb5,0xbfe2bfb5,0xbff5bfb5,0x3e493ffb,0x3fa23ec8,0x3fff3ec8,0xbfc6bffb,
0xbfa2bfed,0x3fff3fed,0xbfc63f44,0x3e49bf44,0x3ff53f8e,0x3f713fd5,0x3f15bfd5,0x3fe23f8e,0xbf44c000,0xbfedc000,0xbfed0000,0xbf440000,
0x3fed3fb5,0xbf44bfb5,0x3f44bfb5,0xbfedbfb5,0xbfed0000,0x3f440000,0x3f444000,0xbfedc000,0x3f44bfb5,0x3fed3fb5,0xbfedbfb5,0xbf44bfb5,
0xbff5bfb5,0xbfe2bfb5,0xbf153fb5,0x3f713fb5,0x3fc6bec8,0xbfffbffb,0xbfa2bffb,0xbe493ec8,0x3e493fed,0xbfc6bfed,0x3fff3f44,0xbfa2bf44,
0xbfe2bfd5,0xbf15bf8e,0xbf713f8e,0xbff5bfd5,0xbfd50000,0xbec80000,0x3f8e4000,0x3ffb4000,0xbec8bfed,0xbf8ebf44,0xbffbbf44,0x3fd53fed,
0x3ffb3fb5,0xbfd5bfb5,0x3ec8bfb5,0x3f8e3fb5,0xbf8e3f44,0xbffbbfed,0x3fd53fed,0x3ec83f44,0xbe493fb5,0x3fa23fb5,0x3fff3fb5,0x3fc63fb5,
0xbff5bfd5,0x3f713f8e,0xbf153f8e,0x3fe23fd5,0x3f71bf44,0x3f153f44,0xbfe2bfed,0x3ff53fed,0x3fc63ffb,0x3e493ec8,0x3fa2bec8,0x3fff3ffb,
0x40004000,0x3fb54000,0x0,0xbfb50000,0x40004000,0xbfb50000,0x0,0xbfb5c000,0x40004000,0xbfb5c000,0x0,0x3fb50000,
0x40004000,0x3fb50000,0x0,0x3fb54000,0xbe490000,0xbfc60000,0xbfffc000,0xbfa2c000,0xbf15bec8,0xbf71bffb,0xbff5bffb,0x3fe23ec8,
0xbf71bf44,0x3ff53f44,0xbfe2bfed,0x3f153fed,0xbfa2bf8e,0x3e493fd5,0xbfc6bfd5,0xbfffbf8e,0xbffbc000,0xbf8ec000,0x3ec80000,0x3fd50000,
0xbfd5bfed,0x3ffb3f44,0x3f8e3f44,0x3ec83fed,0xbf8ebfb5,0xbec83fb5,0x3fd53fb5,0xbffbbfb5,0xbec8bf44,0xbfd5bfed,0x3ffb3fed,0x3f8ebf44,
0x3f150000,0x3fe20000,0x3ff54000,0x3f714000,0x3fc63f8e,0xbe493fd5,0x3fa23fd5,0xbfffbf8e,0x3fff3fed,0xbfc6bfed,0x3e493f44,0x3fa2bf44,
0x3fe23ffb,0x3ff53ec8,0xbf71bec8,0x3f153ffb,0x3fed4000,0x3f444000,0xbf440000,0xbfed0000,0x3f443fb5,0xbfedbfb5,0xbfedbfb5,0x3f44bfb5,
0xbf440000,0x3fed0000,0xbfedc000,0x3f444000,0xbfedbfb5,0xbf443fb5,0xbf44bfb5,0xbfedbfb5,0xbf710000,0xbff50000,0xbfe2c000,0xbf15c000,
0xbfffbfd5,0x3fa2bf8e,0xbe49bf8e,0x3fc63fd5,0xbfa2bfed,0xbe493fed,0x3fc63f44,0xbfffbf44,0x3f15bec8,0xbf71bffb,0x3ff53ffb,0x3fe2bec8,
0xbfd5c000,0xbec8c000,0x3f8e0000,0x3ffb0000,0x3ec8bf44,0x3f8e3fed,0x3ffb3fed,0xbfd53f44,0x3ffb3fb5,0xbfd5bfb5,0x3ec83fb5,0x3f8ebfb5,
0x3f8e3fed,0x3ffb3f44,0xbfd5bf44,0xbec83fed,0x3fa20000,0x3fff0000,0x3fc64000,0x3e494000,0x3fe23ffb,0xbff53ec8,0xbf713ec8,0xbf15bffb,
0xbf153f44,0x3fe2bf44,0xbff5bfed,0x3f713fed,0xbfffbfd5,0xbfc63f8e,0x3e49bf8e,0xbfa2bfd5,0x4000,0xbfb54000,0xc0000000,0xbfb50000,
0xc000,0x3fb50000,0x40000000,0xbfb54000,0x4000,0x3fb5c000,0xc0000000,0x3fb50000,0xc000,0xbfb50000,0x40000000,0x3fb5c000,
0xbfff0000,0xbfa20000,0x3e49c000,0x3fc6c000,0x3ff53ec8,0xbfe23ffb,0xbf153ffb,0xbf71bec8,0xbfe2bf44,0x3f153f44,0x3f71bfed,0xbff53fed,
0x3fc63f8e,0x3fffbfd5,0xbfa23fd5,0x3e493f8e,0x3ec8c000,0x3fd5c000,0x3ffb0000,0x3f8e0000,0xbf8e3fed,0xbec8bf44,0xbfd5bf44,0x3ffbbfed,
0x3fd5bfb5,0xbffb3fb5,0x3f8e3fb5,0x3ec8bfb5,0xbffb3f44,0xbf8e3fed,0xbec8bfed,0xbfd53f44,0x3ff50000,0x3f710000,0xbf154000,0xbfe24000,
0xbfa2bf8e,0x3fffbfd5,0x3fc6bfd5,0xbe493f8e,0x3e493fed,0x3fa2bfed,0xbfff3f44,0x3fc6bf44,0x3f71bffb,0xbf15bec8,0x3fe23ec8,0x3ff5bffb,
0xbf444000,0xbfed4000,0xbfed0000,0xbf440000,0x3fedbfb5,0xbf443fb5,0x3f443fb5,0xbfed3fb5,0xbfed0000,0x3f440000,0x3f44c000,0xbfed4000,
0x3f443fb5,0x3fedbfb5,0xbfed3fb5,0xbf443fb5,0xbfe20000,0xbf150000,0x3f71c000,0x3ff5c000,0x3e493fd5,0xbfc63f8e,0xbfff3f8e,0x3fa2bfd5,
0x3fc6bfed,0xbfff3fed,0x3fa23f44,0x3e49bf44,0xbff53ec8,0xbfe23ffb,0x3f15bffb,0xbf713ec8,0x3f8ec000,0x3ffbc000,0x3fd50000,0x3ec80000,
0xbffb3f44,0x3fd5bfed,0x3ec8bfed,0x3f8ebf44,0x3ec83fb5,0x3f8ebfb5,0xbffb3fb5,0x3fd5bfb5,0x3fd5bfed,0x3ec8bf44,0x3f8e3f44,0x3ffbbfed,
0x3fc60000,0x3e490000,0xbfa24000,0xbfff4000,0x3f71bffb,0x3f15bec8,0x3fe2bec8,0xbff53ffb,0xbff53f44,0x3f71bf44,0x3f15bfed,0xbfe23fed,
0xbe493fd5,0x3fa2bf8e,0xbfff3f8e,0xbfc63fd5,0xc0004000,0xbfb54000,0x0,0x3fb50000,0xc0004000,0x3fb50000,0x0,0x3fb5c000,
0xc0004000,0x3fb5c000,0x0,0xbfb50000,0xc0004000,0xbfb50000,0x0,0xbfb54000,0x3e490000,0x3fc60000,0x3fffc000,0x3fa2c000,
0x3f15bec8,0x3f71bffb,0x3ff5bffb,0xbfe23ec8,0x3f71bf44,0xbff53f44,0x3fe2bfed,0xbf153fed,0x3fa2bf8e,0xbe493fd5,0x3fc6bfd5,0x3fffbf8e,
0x3ffbc000,0x3f8ec000,0xbec80000,0xbfd50000,0x3fd5bfed,0xbffb3f44,0xbf8e3f44,0xbec83fed,0x3f8ebfb5,0x3ec83fb5,0xbfd53fb5,0x3ffbbfb5,
0x3ec8bf44,0x3fd5bfed,0xbffb3fed,0xbf8ebf44,0xbf150000,0xbfe20000,0xbff54000,0xbf714000,0xbfc63f8e,0x3e493fd5,0xbfa23fd5,0x3fffbf8e,
0xbfff3fed,0x3fc6bfed,0xbe493f44,0xbfa2bf44,0xbfe23ffb,0xbff53ec8,0x3f71bec8,0xbf153ffb,0xbfed4000,0xbf444000,0x3f440000,0x3fed0000,
0xbf443fb5,0x3fedbfb5,0x3fedbfb5,0xbf44bfb5,0x3f440000,0xbfed0000,0x3fedc000,0xbf444000,0x3fedbfb5,0x3f443fb5,0x3f44bfb5,0x3fedbfb5,
0x3f710000,0x3ff50000,0x3fe2c000,0x3f15c000,0x3fffbfd5,0xbfa2bf8e,0x3e49bf8e,0xbfc63fd5,0x3fa2bfed,0x3e493fed,0xbfc63f44,0x3fffbf44,
0xbf15bec8,0x3f71bffb,0xbff53ffb,0xbfe2bec8,0x3fd5c000,0x3ec8c000,0xbf8e0000,0xbffb0000,0xbec8bf44,0xbf8e3fed,0xbffb3fed,0x3fd53f44,
0xbffb3fb5,0x3fd5bfb5,0xbec83fb5,0xbf8ebfb5,0xbf8e3fed,0xbffb3f44,0x3fd5bf44,0x3ec83fed,0xbfa20000,0xbfff0000,0xbfc64000,0xbe494000,
0xbfe23ffb,0x3ff53ec8,0x3f713ec8,0x3f15bffb,0x3f153f44,0xbfe2bf44,0x3ff5bfed,0xbf713fed,0x3fffbfd5,0x3fc63f8e,0xbe49bf8e,0x3fa2bfd5,
0x4000,0x3fb54000,0x40000000,0x3fb50000,0xc000,0xbfb50000,0xc0000000,0x3fb54000,0x4000,0xbfb5c000,0x40000000,0xbfb50000,
0xc000,0x3fb50000,0xc0000000,0xbfb5c000,0x3fff0000,0x3fa20000,0xbe49c000,0xbfc6c000,0xbff53ec8,0x3fe23ffb,0x3f153ffb,0x3f71bec8,
0x3fe2bf44,0xbf153f44,0xbf71bfed,0x3ff53fed,0xbfc63f8e,0xbfffbfd5,0x3fa23fd5,0xbe493f8e,0xbec8c000,0xbfd5c000,0xbffb0000,0xbf8e0000,
0x3f8e3fed,0x3ec8bf44,0x3fd5bf44,0xbffbbfed,0xbfd5bfb5,0x3ffb3fb5,0xbf8e3fb5,0xbec8bfb5,0x3ffb3f44,0x3f8e3fed,0x3ec8bfed,0x3fd53f44,
0xbff50000,0xbf710000,0x3f154000,0x3fe24000,0x3fa2bf8e,0xbfffbfd5,0xbfc6bfd5,0x3e493f8e,0xbe493fed,0xbfa2bfed,0x3fff3f44,0xbfc6bf44,
0xbf71bffb,0x3f15bec8,0xbfe23ec8,0xbff5bffb,0x3f444000,0x3fed4000,0x3fed0000,0x3f440000,0xbfedbfb5,0x3f443fb5,0xbf443fb5,0x3fed3fb5,
0x3fed0000,0xbf440000,0xbf44c000,0x3fed4000,0xbf443fb5,0xbfedbfb5,0x3fed3fb5,0x3f443fb5,0x3fe20000,0x3f150000,0xbf71c000,0xbff5c000,
0xbe493fd5,0x3fc63f8e,0x3fff3f8e,0xbfa2bfd5,0xbfc6bfed,0x3fff3fed,0xbfa23f44,0xbe49bf44,0x3ff53ec8,0x3fe23ffb,0xbf15bffb,0x3f713ec8,
0xbf8ec000,0xbffbc000,0xbfd50000,0xbec80000,0x3ffb3f44,0xbfd5bfed,0xbec8bfed,0xbf8ebf44,0xbec83fb5,0xbf8ebfb5,0x3ffb3fb5,0xbfd5bfb5,
0xbfd5bfed,0xbec8bf44,0xbf8e3f44,0xbffbbfed,0xbfc60000,0xbe490000,0x3fa24000,0x3fff4000,0xbf71bffb,0xbf15bec8,0xbfe2bec8,0x3ff53ffb,
0x3ff53f44,0xbf71bf44,0xbf15bfed,0x3fe23fed,0x3e493fd5,0xbfa2bf8e,0x3fff3f8e,0x3fc63fd5,0x40004000,0x3fb54000,0x0,0xbfb50000,
0x40004000,0xbfb50000,0x0,0xbfb5c000,0x40004000,0xbfb5c000,0x0,0x3fb50000,0x40004000,0x3fb50000,0x0,0x3fb54000,
0xbfc6bfb5,0xbfffbfb5,0xbfa2bfb5,0x3e49bfb5,0xbfe2bfd5,0x3f15bf8e,0xbf71bf8e,0x3ff53fd5,0xbff5bfed,0x3fe23fed,0xbf15bf44,0xbf713f44,
0xbfffbffb,0xbfa23ec8,0xbe49bec8,0xbfc6bffb,0x3ec80000,0x3fd50000,0x3ffb4000,0x3f8e4000,0x3f8e3f44,0x3ec83fed,0x3fd53fed,0xbffbbf44,
0x3fd53fb5,0xbffbbfb5,0x3f8e3fb5,0x3ec8bfb5,0x3ffb3fed,0x3f8ebf44,0x3ec83f44,0x3fd53fed,0x3f713fb5,0xbf153fb5,0xbfe2bfb5,0xbff5bfb5,
0xbe493ec8,0xbfa2bffb,0xbfffbffb,0x3fc6bec8,0xbfa2bf44,0x3fff3f44,0xbfc6bfed,0x3e493fed,0xbff5bfd5,0xbf713f8e,0xbf15bf8e,0xbfe2bfd5,
0xbfedc000,0xbf44c000,0x3f440000,0x3fed0000,0xbf44bfb5,0x3fed3fb5,0x3fed3fb5,0xbf443fb5,0x3f440000,0xbfed0000,0x3fed4000,0xbf44c000,
0x3fed3fb5,0x3f44bfb5,0x3f443fb5,0x3fed3fb5,0x3ff53fb5,0x3fe23fb5,0x3f153fb5,0xbf713fb5,0x3fc63ffb,0xbfffbec8,0xbfa2bec8,0xbe49bffb,
0xbe493f44,0x3fc6bf44,0xbfffbfed,0x3fa23fed,0xbfe2bf8e,0xbf153fd5,0xbf71bfd5,0xbff5bf8e,0xbf8e0000,0xbffb0000,0xbfd5c000,0xbec8c000,
0xbffbbfed,0x3fd5bf44,0x3ec8bf44,0x3f8e3fed,0xbec8bfb5,0xbf8e3fb5,0x3ffb3fb5,0xbfd5bfb5,0x3fd53f44,0x3ec8bfed,0x3f8e3fed,0x3ffb3f44,
0xbe49bfb5,0x3fa2bfb5,0x3fff3fb5,0x3fc63fb5,0x3ff53f8e,0xbf713fd5,0x3f153fd5,0xbfe2bf8e,0x3f713fed,0x3f15bfed,0xbfe2bf44,0x3ff53f44,
0xbfc6bec8,0xbe493ffb,0xbfa2bffb,0xbfffbec8,0x4000,0xbfb54000,0xc0000000,0xbfb50000,0xc000,0x3fb50000,0x40000000,0xbfb54000,
0x4000,0x3fb5c000,0xc0000000,0x3fb50000,0xc000,0xbfb50000,0x40000000,0x3fb5c000,0xbfa2bfb5,0x3e49bfb5,0x3fc6bfb5,0x3fffbfb5,
0x3f713fd5,0xbff53f8e,0xbfe23f8e,0x3f15bfd5,0xbf15bfed,0xbf713fed,0x3ff5bf44,0xbfe23f44,0x3e493ffb,0x3fc6bec8,0xbfff3ec8,0xbfa23ffb,
0x3ffb0000,0x3f8e0000,0xbec84000,0xbfd54000,0xbfd5bf44,0x3ffbbfed,0x3f8ebfed,0x3ec83f44,0x3f8e3fb5,0x3ec8bfb5,0xbfd53fb5,0x3ffbbfb5,
0xbec8bfed,0xbfd53f44,0x3ffbbf44,0x3f8ebfed,0xbfe23fb5,0xbff53fb5,0xbf71bfb5,0x3f15bfb5,0x3fffbec8,0xbfc63ffb,0xbe493ffb,0xbfa23ec8,
0xbfc6bf44,0x3e493f44,0x3fa2bfed,0xbfff3fed,0x3f153fd5,0x3fe2bf8e,0xbff53f8e,0xbf713fd5,0x3f44c000,0x3fedc000,0x3fed0000,0x3f440000,
0xbfed3fb5,0x3f44bfb5,0xbf44bfb5,0x3fedbfb5,0x3fed0000,0xbf440000,0xbf444000,0x3fedc000,0xbf44bfb5,0xbfed3fb5,0x3fedbfb5,0x3f44bfb5,
0x3f153fb5,0xbf713fb5,0xbff53fb5,0xbfe23fb5,0x3fa2bffb,0x3e493ec8,0x3fc63ec8,0xbfff3ffb,0xbfff3f44,0x3fa2bf44,0x3e49bfed,0xbfc63fed,
0x3f713f8e,0x3ff5bfd5,0xbfe23fd5,0xbf153f8e,0xbfd50000,0xbec80000,0x3f8ec000,0x3ffbc000,0xbec83fed,0xbf8e3f44,0xbffb3f44,0x3fd5bfed,
0x3ffbbfb5,0xbfd53fb5,0x3ec83fb5,0x3f8ebfb5,0xbf8ebf44,0xbffb3fed,0x3fd5bfed,0x3ec8bf44,0x3fffbfb5,0x3fc6bfb5,0x3e493fb5,0xbfa23fb5,
0xbf15bf8e,0x3fe2bfd5,0x3ff5bfd5,0xbf713f8e,0xbfe23fed,0x3ff5bfed,0xbf71bf44,0xbf153f44,0x3fa23ec8,0x3fffbffb,0xbfc63ffb,0xbe493ec8,
0xc0004000,0xbfb54000,0x0,0x3fb50000,0xc0004000,0x3fb50000,0x0,0x3fb5c000,0xc0004000,0x3fb5c000,0x0,0xbfb50000,
0xc0004000,0xbfb50000,0x0,0xbfb54000,0x3fc6bfb5,0x3fffbfb5,0x3fa2bfb5,0xbe49bfb5,0x3fe2bfd5,0xbf15bf8e,0x3f71bf8e,0xbff53fd5,
0x3ff5bfed,0xbfe23fed,0x3f15bf44,0x3f713f44,0x3fffbffb,0x3fa23ec8,0x3e49bec8,0x3fc6bffb,0xbec80000,0xbfd50000,0xbffb4000,0xbf8e4000,
0xbf8e3f44,0xbec83fed,0xbfd53fed,0x3ffbbf44,0xbfd53fb5,0x3ffbbfb5,0xbf8e3fb5,0xbec8bfb5,0xbffb3fed,0xbf8ebf44,0xbec83f44,0xbfd53fed,
0xbf713fb5,0x3f153fb5,0x3fe2bfb5,0x3ff5bfb5,0x3e493ec8,0x3fa2bffb,0x3fffbffb,0xbfc6bec8,0x3fa2bf44,0xbfff3f44,0x3fc6bfed,0xbe493fed,
0x3ff5bfd5,0x3f713f8e,0x3f15bf8e,0x3fe2bfd5,0x3fedc000,0x3f44c000,0xbf440000,0xbfed0000,0x3f44bfb5,0xbfed3fb5,0xbfed3fb5,0x3f443fb5,
0xbf440000,0x3fed0000,0xbfed4000,0x3f44c000,0xbfed3fb5,0xbf44bfb5,0xbf443fb5,0xbfed3fb5,0xbff53fb5,0xbfe23fb5,0xbf153fb5,0x3f713fb5,
0xbfc63ffb,0x3fffbec8,0x3fa2bec8,0x3e49bffb,0x3e493f44,0xbfc6bf44,0x3fffbfed,0xbfa23fed,0x3fe2bf8e,0x3f153fd5,0x3f71bfd5,0x3ff5bf8e,
0x3f8e0000,0x3ffb0000,0x3fd5c000,0x3ec8c000,0x3ffbbfed,0xbfd5bf44,0xbec8bf44,0xbf8e3fed,0x3ec8bfb5,0x3f8e3fb5,0xbffb3fb5,0x3fd5bfb5,
0xbfd53f44,0xbec8bfed,0xbf8e3fed,0xbffb3f44,0x3e49bfb5,0xbfa2bfb5,0xbfff3fb5,0xbfc63fb5,0xbff53f8e,0x3f713fd5,0xbf153fd5,0x3fe2bf8e,
0xbf713fed,0xbf15bfed,0x3fe2bf44,0xbff53f44,0x3fc6bec8,0x3e493ffb,0x3fa2bffb,0x3fffbec8,0x4000,0x3fb54000,0x40000000,0x3fb50000,
0xc000,0xbfb50000,0xc0000000,0x3fb54000,0x4000,0xbfb5c000,0x40000000,0xbfb50000,0xc000,0x3fb50000,0xc0000000,0xbfb5c000,
0x3fa2bfb5,0xbe49bfb5,0xbfc6bfb5,0xbfffbfb5,0xbf713fd5,0x3ff53f8e,0x3fe23f8e,0xbf15bfd5,0x3f15bfed,0x3f713fed,0xbff5bf44,0x3fe23f44,
0xbe493ffb,0xbfc6bec8,0x3fff3ec8,0x3fa23ffb,0xbffb0000,0xbf8e0000,0x3ec84000,0x3fd54000,0x3fd5bf44,0xbffbbfed,0xbf8ebfed,0xbec83f44,
0xbf8e3fb5,0xbec8bfb5,0x3fd53fb5,0xbffbbfb5,0x3ec8bfed,0x3fd53f44,0xbffbbf44,0xbf8ebfed,0x3fe23fb5,0x3ff53fb5,0x3f71bfb5,0xbf15bfb5,
0xbfffbec8,0x3fc63ffb,0x3e493ffb,0x3fa23ec8,0x3fc6bf44,0xbe493f44,0xbfa2bfed,0x3fff3fed,0xbf153fd5,0xbfe2bf8e,0x3ff53f8e,0x3f713fd5,
0xbf44c000,0xbfedc000,0xbfed0000,0xbf440000,0x3fed3fb5,0xbf44bfb5,0x3f44bfb5,0xbfedbfb5,0xbfed0000,0x3f440000,0x3f444000,0xbfedc000,
0x3f44bfb5,0x3fed3fb5,0xbfedbfb5,0xbf44bfb5,0xbf153fb5,0x3f713fb5,0x3ff53fb5,0x3fe23fb5,0xbfa2bffb,0xbe493ec8,0xbfc63ec8,0x3fff3ffb,
0x3fff3f44,0xbfa2bf44,0xbe49bfed,0x3fc63fed,0xbf713f8e,0xbff5bfd5,0x3fe23fd5,0x3f153f8e,0x3fd50000,0x3ec80000,0xbf8ec000,0xbffbc000,
0x3ec83fed,0x3f8e3f44,0x3ffb3f44,0xbfd5bfed,0xbffbbfb5,0x3fd53fb5,0xbec83fb5,0xbf8ebfb5,0x3f8ebf44,0x3ffb3fed,0xbfd5bfed,0xbec8bf44,
0xbfffbfb5,0xbfc6bfb5,0xbe493fb5,0x3fa23fb5,0x3f15bf8e,0xbfe2bfd5,0xbff5bfd5,0x3f713f8e,0x3fe23fed,0xbff5bfed,0x3f71bf44,0x3f153f44,
0xbfa23ec8,0xbfffbffb,0x3fc63ffb,0x3e493ec8,0x80003f80,0x3f800000,0x80003f80,0x3f800000,0x80003f80,0x3f800000,0x80003f80,0x3f800000,
0x80003f80,0x3f800000,0x80003f80,0x3f800000,0x80003f80,0x3f800000,0x80003f80,0x3f800000,0x80003f80,0x3f800000,0x8000bf80,0xbf800000,
0x3f353f35,0x3f35bf35,0xbf35bf35,0xbf353f35,0x3f800000,0xbf80,0xbf800000,0x3f80,0x3f35bf35,0xbf35bf35,0xbf353f35,0x3f353f35,
0x80003f80,0x3f800000,0x80003f80,0x3f800000,0x3f800000,0xbf80,0x3f800000,0xbf80,0x8000bf80,0xbf800000,0x8000bf80,0xbf800000,
0xbf800000,0x3f80,0xbf800000,0x3f80,0x80003f80,0x3f800000,0x8000bf80,0xbf800000,0x3f35bf35,0xbf35bf35,0xbf353f35,0x3f353f35,
0xbf800000,0x3f80,0x3f800000,0xbf80,0x3f353f35,0x3f35bf35,0xbf35bf35,0xbf353f35,0x80003f80,0x3f800000,0x80003f80,0x3f800000,
0x8000bf80,0xbf800000,0x8000bf80,0xbf800000,0x80003f80,0x3f800000,0x80003f80,0x3f800000,0x8000bf80,0xbf800000,0x8000bf80,0xbf800000,
0x80003f80,0x3f800000,0x8000bf80,0xbf800000,0xbf35bf35,0xbf353f35,0x3f353f35,0x3f35bf35,0x3f800000,0xbf80,0xbf800000,0x3f80,
0xbf353f35,0x3f353f35,0x3f35bf35,0xbf35bf35,0x80003f80,0x3f800000,0x80003f80,0x3f800000,0xbf800000,0x3f80,0xbf800000,0x3f80,
0x8000bf80,0xbf800000,0x8000bf80,0xbf800000,0x3f800000,0xbf80,0x3f800000,0xbf80,0x80003f80,0x3f800000,0x8000bf80,0xbf800000,
0xbf353f35,0x3f353f35,0x3f35bf35,0xbf35bf35,0xbf800000,0x3f80,0x3f800000,0xbf80,0xbf35bf35,0xbf353f35,0x3f353f35,0x3f35bf35,
0x3f803f80,0x80008000,0x80008000,0xbf80bf80,0x3f803f80,0x80008000,0x80008000,0xbf80bf80,0x3f803f80,0x80008000,0x80008000,0xbf80bf80,
0x3f803f80,0x80008000,0x80008000,0xbf80bf80,0x3f353f80,0x3f358000,0x3f358000,0xbf35bf80,0xbf350000,0x3f353f80,0x3f353f80,0x3f358000,
0xbf35bf80,0xbf358000,0xbf358000,0x3f353f80,0x3f350000,0xbf35bf80,0xbf35bf80,0xbf358000,0x3f80,0x3f808000,0x3f808000,0x8000bf80,
0xbf80,0xbf808000,0xbf808000,0x80003f80,0x3f80,0x3f808000,0x3f808000,0x8000bf80,0xbf80,0xbf808000,0xbf808000,0x80003f80,
0xbf353f80,0x3f358000,0x3f358000,0x3f35bf80,0x3f350000,0x3f35bf80,0x3f35bf80,0xbf358000,0x3f35bf80,0xbf358000,0xbf358000,0xbf353f80,
0xbf350000,0xbf353f80,0xbf353f80,0x3f358000,0xbf803f80,0x80008000,0x80008000,0x3f80bf80,0xbf803f80,0x80008000,0x80008000,0x3f80bf80,
0xbf803f80,0x80008000,0x80008000,0x3f80bf80,0xbf803f80,0x80008000,0x80008000,0x3f80bf80,0xbf353f80,0xbf358000,0xbf358000,0x3f35bf80,
0x3f350000,0xbf353f80,0xbf353f80,0xbf358000,0x3f35bf80,0x3f358000,0x3f358000,0xbf353f80,0xbf350000,0x3f35bf80,0x3f35bf80,0x3f358000,
0x3f80,0xbf808000,0xbf808000,0x8000bf80,0xbf80,0x3f808000,0x3f808000,0x80003f80,0x3f80,0xbf808000,0xbf808000,0x8000bf80,
0xbf80,0x3f808000,0x3f808000,0x80003f80,0x3f353f80,0xbf358000,0xbf358000,0xbf35bf80,0xbf350000,0xbf35bf80,0xbf35bf80,0x3f358000,
0xbf35bf80,0x3f358000,0x3f358000,0x3f353f80,0x3f350000,0x3f353f80,0x3f353f80,0xbf358000,0x3f800000,0x0,0x3f800000,0x0,
0x3f800000,0x0,0x3f800000,0x0,0x3f800000,0x0,0x3f800000,0x0,0x3f800000,0x0,0x3f800000,0x0,
0x3f800000,0x0,0x3f7fb10f,0xbd48fb30,0x3f7ec46d,0xbdc8bd36,0x3f7d3aac,0xbe164083,0x3f7b14be,0xbe47c5c2,0x3f7853f8,0xbe78cfcc,
0x3f74fa0b,0xbe94a031,0x3f710908,0xbeac7cd4,0x3f800000,0x0,0x3f7ec46d,0xbdc8bd36,0x3f7b14be,0xbe47c5c2,0x3f74fa0b,0xbe94a031,
0x3f6c835e,0xbec3ef15,0x3f61c598,0xbef15aea,0x3f54db31,0xbf0e39da,0x3f45e403,0xbf226799,0x3f800000,0x0,0x3f7d3aac,0xbe164083,
0x3f74fa0b,0xbe94a031,0x3f676bd8,0xbedae880,0x3f54db31,0xbf0e39da,0x3f3daef9,0xbf2beb4a,0x3f226799,0xbf45e403,0x3f039c3d,0xbf5b941a,
0x3f800000,0x0,0x3f7b14be,0xbe47c5c2,0x3f6c835e,0xbec3ef15,0x3f54db31,0xbf0e39da,0x3f3504f3,0xbf3504f3,0x3f0e39da,0xbf54db31,
0x3ec3ef15,0xbf6c835e,0x3e47c5c2,0xbf7b14be,0x3f800000,0x0,0x3f7853f8,0xbe78cfcc,0x3f61c598,0xbef15aea,0x3f3daef9,0xbf2beb4a,
0x3f0e39da,0xbf54db31,0x3eac7cd4,0xbf710908,0x3dc8bd36,0xbf7ec46d,0xbe164083,0xbf7d3aac,0x3f800000,0x0,0x3f74fa0b,0xbe94a031,
0x3f54db31,0xbf0e39da,0x3f226799,0xbf45e403,0x3ec3ef15,0xbf6c835e,0x3dc8bd36,0xbf7ec46d,0xbe47c5c2,0xbf7b14be,0xbef15aea,0xbf61c598,
0x3f800000,0x0,0x3f710908,0xbeac7cd4,0x3f45e403,0xbf226799,0x3f039c3d,0xbf5b941a,0x3e47c5c2,0xbf7b14be,0xbe164083,0xbf7d3aac,
0xbef15aea,0xbf61c598,0xbf3daef9,0xbf2beb4a,0x3f800000,0x0,0x3f800000,0x0,0x3f800000,0x0,0x3f800000,0x0,
0x3f800000,0x0,0x3f800000,0x0,0x3f800000,0x0,0x3f800000,0x0,0x3f6c835e,0xbec3ef15,0x3f676bd8,0xbedae880,
0x3f61c598,0xbef15aea,0x3f5b941a,0xbf039c3d,0x3f54db31,0xbf0e39da,0x3f4d9f02,0xbf187fc0,0x3f45e403,0xbf226799,0x3f3daef9,0xbf2beb4a,
0x3f3504f3,0xbf3504f3,0x3f226799,0xbf45e403,0x3f0e39da,0xbf54db31,0x3ef15aea,0xbf61c598,0x3ec3ef15,0xbf6c835e,0x3e94a031,0xbf74fa0b,
0x3e47c5c2,0xbf7b14be,0x3dc8bd36,0xbf7ec46d,0x3ec3ef15,0xbf6c835e,0x3e78cfcc,0xbf7853f8,0x3dc8bd36,0xbf7ec46d,0xbd48fb30,0xbf7fb10f,
0xbe47c5c2,0xbf7b14be,0xbeac7cd4,0xbf710908,0xbef15aea,0xbf61c598,0xbf187fc0,0xbf4d9f02,0x0,0xbf800000,0xbe47c5c2,0xbf7b14be,
0xbec3ef15,0xbf6c835e,0xbf0e39da,0xbf54db31,0xbf3504f3,0xbf3504f3,0xbf54db31,0xbf0e39da,0xbf6c835e,0xbec3ef15,0xbf7b14be,0xbe47c5c2,
0xbec3ef15,0xbf6c835e,0xbf187fc0,0xbf4d9f02,0xbf45e403,0xbf226799,0xbf676bd8,0xbedae880,0xbf7b14be,0xbe47c5c2,0xbf7fb10f,0x3d48fb30,
0xbf74fa0b,0x3e94a031,0xbf5b941a,0x3f039c3d,0xbf3504f3,0xbf3504f3,0xbf61c598,0xbef15aea,0xbf7b14be,0xbe47c5c2,0xbf7ec46d,0x3dc8bd36,
0xbf6c835e,0x3ec3ef15,0xbf45e403,0x3f226799,0xbf0e39da,0x3f54db31,0xbe94a031,0x3f74fa0b,0xbf6c835e,0xbec3ef15,0xbf7fb10f,0xbd48fb30,
0xbf74fa0b,0x3e94a031,0xbf4d9f02,0x3f187fc0,0xbf0e39da,0x3f54db31,0xbe78cfcc,0x3f7853f8,0x3dc8bd36,0x3f7ec46d,0x3edae880,0x3f676bd8,
0x80003f80,0x3f800000,0x3f800000,0xbf80,0x3ec43f6d,0x3f6dbec4,0x3f6dbec4,0xbec4bf6d,0x3f353f35,0x3f35bf35,0x3f35bf35,0xbf35bf35,
0x3f6d3ec4,0x3ec4bf6d,0x3ec4bf6d,0xbf6dbec4,0x80003f80,0x3f800000,0xbf800000,0x3f80,0x3f6d3ec4,0x3ec4bf6d,0xbec43f6d,0x3f6d3ec4,
0x3f35bf35,0xbf35bf35,0x3f353f35,0x3f35bf35,0xbec4bf6d,0xbf6d3ec4,0x3f6dbec4,0xbec4bf6d,0x80003f80,0x3f800000,0x3f800000,0xbf80,
0x3f6dbec4,0xbec4bf6d,0xbec4bf6d,0xbf6d3ec4,0xbf35bf35,0xbf353f35,0xbf353f35,0x3f353f35,0xbec43f6d,0x3f6d3ec4,0x3f6d3ec4,0x3ec4bf6d,
0x80003f80,0x3f800000,0xbf800000,0x3f80,0x3ec4bf6d,0xbf6dbec4,0x3f6d3ec4,0x3ec4bf6d,0xbf353f35,0x3f353f35,0xbf35bf35,0xbf353f35,
0x3f6dbec4,0xbec4bf6d,0x3ec43f6d,0x3f6dbec4,0x80003f80,0x3f800000,0x3f800000,0xbf80,0xbec4bf6d,0xbf6d3ec4,0xbf6d3ec4,0x3ec43f6d,
0x3f353f35,0x3f35bf35,0x3f35bf35,0xbf35bf35,0xbf6dbec4,0xbec43f6d,0xbec43f6d,0x3f6d3ec4,0x80003f80,0x3f800000,0xbf800000,0x3f80,
0xbf6dbec4,0xbec43f6d,0x3ec4bf6d,0xbf6dbec4,0x3f35bf35,0xbf35bf35,0x3f353f35,0x3f35bf35,0x3ec43f6d,0x3f6dbec4,0xbf6d3ec4,0x3ec43f6d,
0x80003f80,0x3f800000,0x3f800000,0xbf80,0xbf6d3ec4,0x3ec43f6d,0x3ec43f6d,0x3f6dbec4,0xbf35bf35,0xbf353f35,0xbf353f35,0x3f353f35,
0x3ec4bf6d,0xbf6dbec4,0xbf6dbec4,0xbec43f6d,0x80003f80,0x3f800000,0xbf800000,0x3f80,0xbec43f6d,0x3f6d3ec4,0xbf6dbec4,0xbec43f6d,
0xbf353f35,0x3f353f35,0xbf35bf35,0xbf353f35,0xbf6d3ec4,0x3ec43f6d,0xbec4bf6d,0xbf6d3ec4,0x3f803f80,0x80008000,0x80008000,0xbf80bf80,
0x3f803f80,0x80008000,0x80008000,0xbf80bf80,0x3f803f80,0x80008000,0x80008000,0xbf80bf80,0x3f803f80,0x80008000,0x80008000,0xbf80bf80,
0x3ec43f6d,0x3f6d3ec4,0x3f6d3ec4,0xbec4bf6d,0xbf6dbec4,0x3ec43f6d,0x3ec43f6d,0x3f6d3ec4,0xbec4bf6d,0xbf6dbec4,0xbf6dbec4,0x3ec43f6d,
0x3f6d3ec4,0xbec4bf6d,0xbec4bf6d,0xbf6dbec4,0xbf353f35,0x3f353f35,0x3f353f35,0x3f35bf35,0x3f35bf35,0xbf35bf35,0xbf35bf35,0xbf353f35,
0xbf353f35,0x3f353f35,0x3f353f35,0x3f35bf35,0x3f35bf35,0xbf35bf35,0xbf35bf35,0xbf353f35,0xbf6d3ec4,0xbec43f6d,0xbec43f6d,0x3f6dbec4,
0xbec43f6d,0x3f6dbec4,0x3f6dbec4,0x3ec4bf6d,0x3f6dbec4,0x3ec4bf6d,0x3ec4bf6d,0xbf6d3ec4,0x3ec4bf6d,0xbf6d3ec4,0xbf6d3ec4,0xbec43f6d,
0x0,0xbf803f80,0xbf803f80,0x80008000,0x0,0xbf803f80,0xbf803f80,0x80008000,0x0,0xbf803f80,0xbf803f80,0x80008000,
0x0,0xbf803f80,0xbf803f80,0x80008000,0x3f6dbec4,0xbec43f6d,0xbec43f6d,0xbf6d3ec4,0x3ec4bf6d,0x3f6dbec4,0x3f6dbec4,0xbec43f6d,
0xbf6d3ec4,0x3ec4bf6d,0x3ec4bf6d,0x3f6dbec4,0xbec43f6d,0xbf6d3ec4,0xbf6d3ec4,0x3ec4bf6d,0x3f35bf35,0x3f353f35,0x3f353f35,0xbf353f35,
0xbf353f35,0xbf35bf35,0xbf35bf35,0x3f35bf35,0x3f35bf35,0x3f353f35,0x3f353f35,0xbf353f35,0xbf353f35,0xbf35bf35,0xbf35bf35,0x3f35bf35,
0xbec4bf6d,0x3f6d3ec4,0x3f6d3ec4,0x3ec43f6d,0x3f6d3ec4,0x3ec43f6d,0x3ec43f6d,0xbf6dbec4,0x3ec43f6d,0xbf6dbec4,0xbf6dbec4,0xbec4bf6d,
0xbf6dbec4,0xbec4bf6d,0xbec4bf6d,0x3f6d3ec4,0x3f800000,0x0,0x3f7fec43,0xbcc90ab0,0x3f7fb10f,0xbd48fb30,0x3f7f4e6d,0xbd96a905,
0x3f7ec46d,0xbdc8bd36,0x3f7e1324,0xbdfab273,0x3f7d3aac,0xbe164083,0x3f7c3b28,0xbe2f10a2,0x3f800000,0x0,0x3f7f4e6d,0xbd96a905,
0x3f7d3aac,0xbe164083,0x3f79c79d,0xbe605c13,0x3f74fa0b,0xbe94a031,0x3f6ed89e,0xbeb8442a,0x3f676bd8,0xbedae880,0x3f5ebe05,0xbefc5d27,
0x3f800000,0x0,0x3f7e1324,0xbdfab273,0x3f7853f8,0xbe78cfcc,0x3f6ed89e,0xbeb8442a,0x3f61c598,0xbef15aea,0x3f514d3d,0xbf13682a,
0x3f3daef9,0xbf2beb4a,0x3f273656,0xbf41d870,0x3f800000,0x0,0x3f7c3b28,0xbe2f10a2,0x3f710908,0xbeac7cd4,0x3f5ebe05,0xbefc5d27,
0x3f45e403,0xbf226799,0x3f273656,0xbf41d870,0x3f039c3d,0xbf5b941a,0x3eb8442a,0xbf6ed89e,0x3f800000,0x0,0x3f79c79d,0xbe605c13,
0x3f676bd8,0xbedae880,0x3f49d112,0xbf1d7fd1,0x3f226799,0xbf45e403,0x3ee63375,0xbf64aa59,0x3e78cfcc,0xbf7853f8,0x3cc90ab0,0xbf7fec43,
0x3f800000,0x0,0x3f76ba07,0xbe888e93,0x3f5b941a,0xbf039c3d,0x3f3085bb,0xbf396842,0x3ef15aea,0xbf61c598,0x3e605c13,0xbf79c79d,
0xbd48fb30,0xbf7fb10f,0xbea09ae5,0xbf731447,0x3f800000,0x0,0x3f731447,0xbea09ae5,0x3f4d9f02,0xbf187fc0,0x3f13682a,0xbf514d3d,
0x3e94a031,0xbf74fa0b,0xbcc90ab0,0xbf7fec43,0xbeac7cd4,0xbf710908,0xbf1d7fd1,0xbf49d112,0x3f800000,0x0,0x3f6ed89e,0xbeb8442a,
0x3f3daef9,0xbf2beb4a,0x3ee63375,0xbf64aa59,0x3dc8bd36,0xbf7ec46d,0xbe888e93,0xbf76ba07,0xbf187fc0,0xbf4d9f02,0xbf584853,0xbf08f59b,
0x3f7b14be,0xbe47c5c2,0x3f79c79d,0xbe605c13,0x3f7853f8,0xbe78cfcc,0x3f76ba07,0xbe888e93,0x3f74fa0b,0xbe94a031,0x3f731447,0xbea09ae5,
0x3f710908,0xbeac7cd4,0x3f6ed89e,0xbeb8442a,0x3f54db31,0xbf0e39da,0x3f49d112,0xbf1d7fd1,0x3f3daef9,0xbf2beb4a,0x3f3085bb,0xbf396842,
0x3f226799,0xbf45e403,0x3f13682a,0xbf514d3d,0x3f039c3d,0xbf5b941a,0x3ee63375,0xbf64aa59,0x3f0e39da,0xbf54db31,0x3ee63375,0xbf64aa59,
0x3eac7cd4,0xbf710908,0x3e605c13,0xbf79c79d,0x3dc8bd36,0xbf7ec46d,0xbcc90ab0,0xbf7fec43,0xbe164083,0xbf7d3aac,0xbe888e93,0xbf76ba07,
0x3e47c5c2,0xbf7b14be,0x3cc90ab0,0xbf7fec43,0xbe164083,0xbf7d3aac,0xbea09ae5,0xbf731447,0xbef15aea,0xbf61c598,0xbf1d7fd1,0xbf49d112,
0xbf3daef9,0xbf2beb4a,0xbf584853,0xbf08f59b,0xbe47c5c2,0xbf7b14be,0xbecf7bca,0xbf6a09a7,0xbf187fc0,0xbf4d9f02,0xbf41d870,0xbf273656,
0xbf61c598,0xbef15aea,0xbf76ba07,0xbe888e93,0xbf7fb10f,0xbd48fb30,0xbf7c3b28,0x3e2f10a2,0xbf0e39da,0xbf54db31,0xbf41d870,0xbf273656,
0xbf676bd8,0xbedae880,0xbf7c3b28,0xbe2f10a2,0xbf7ec46d,0x3dc8bd36,0xbf6ed89e,0x3eb8442a,0xbf4d9f02,0x3f187fc0,0xbf1d7fd1,0x3f49d112,
0xbf54db31,0xbf0e39da,0xbf76ba07,0xbe888e93,0xbf7fb10f,0x3d48fb30,0xbf6ed89e,0x3eb8442a,0xbf45e403,0x3f226799,0xbf08f59b,0x3f584853,
0xbe78cfcc,0x3f7853f8,0x3d96a905,0x3f7f4e6d,0xbf7b14be,0xbe47c5c2,0xbf7c3b28,0x3e2f10a2,0xbf5b941a,0x3f039c3d,0xbf1d7fd1,0x3f49d112,
0xbe94a031,0x3f74fa0b,0x3d96a905,0x3f7f4e6d,0x3edae880,0x3f676bd8,0x3f396842,0x3f3085bb,0x80003f80,0x80003f80,0x80003f80,0x80003f80,
0x80003f80,0x80003f80,0x80003f80,0x80003f80,0x80003f80,0x80003f80,0x80003f80,0x80003f80,0x80003f80,0x80003f80,0x80003f80,0x80003f80,
0x3f800000,0x3f800000,0x3f800000,0x3f800000,0x3f800000,0x3f800000,0x3f800000,0x3f800000,0x3f800000,0x3f800000,0x3f800000,0x3f800000,
0x3f800000,0x3f800000,0x3f800000,0x3f800000,0x80003f80,0x3f353f35,0x80003f80,0x3f353f35,0x3f800000,0x3f35bf35,0x3f800000,0x3f35bf35,
0x8000bf80,0xbf35bf35,0x8000bf80,0xbf35bf35,0xbf800000,0xbf353f35,0xbf800000,0xbf353f35,0x3f800000,0x3f35bf35,0x3f800000,0x3f35bf35,
0xbf80,0xbf35bf35,0xbf80,0xbf35bf35,0xbf800000,0xbf353f35,0xbf800000,0xbf353f35,0x3f80,0x3f353f35,0x3f80,0x3f353f35,
0x80003f80,0x3f800000,0x80003f80,0x3f800000,0x8000bf80,0xbf800000,0x8000bf80,0xbf800000,0x80003f80,0x3f800000,0x80003f80,0x3f800000,
0x8000bf80,0xbf800000,0x8000bf80,0xbf800000,0x3f800000,0xbf80,0x3f800000,0xbf80,0xbf800000,0x3f80,0xbf800000,0x3f80,
0x3f800000,0xbf80,0x3f800000,0xbf80,0xbf800000,0x3f80,0xbf800000,0x3f80,0x80003f80,0x3f35bf35,0x80003f80,0x3f35bf35,
0xbf800000,0x3f353f35,0xbf800000,0x3f353f35,0x8000bf80,0xbf353f35,0x8000bf80,0xbf353f35,0x3f800000,0xbf35bf35,0x3f800000,0xbf35bf35,
0x3f800000,0xbf35bf35,0x3f800000,0xbf35bf35,0x3f80,0x3f35bf35,0x3f80,0x3f35bf35,0xbf800000,0x3f353f35,0xbf800000,0x3f353f35,
0xbf80,0xbf353f35,0xbf80,0xbf353f35,0x80003f80,0x3ec43f6d,0x8000bf80,0xbec4bf6d,0x3f353f35,0x3f6d3ec4,0xbf35bf35,0xbf6dbec4,
0x3f800000,0x3f6dbec4,0xbf800000,0xbf6d3ec4,0x3f35bf35,0x3ec4bf6d,0xbf353f35,0xbec43f6d,0x3f800000,0x3f6dbec4,0xbf800000,0xbf6d3ec4,
0x3f35bf35,0x3ec4bf6d,0xbf353f35,0xbec43f6d,0xbf80,0xbec4bf6d,0x3f80,0x3ec43f6d,0xbf35bf35,0xbf6dbec4,0x3f353f35,0x3f6d3ec4,
0x80003f80,0x3f6d3ec4,0x8000bf80,0xbf6dbec4,0x3f35bf35,0xbec4bf6d,0xbf353f35,0x3ec43f6d,0xbf800000,0xbec43f6d,0x3f800000,0x3ec4bf6d,
0x3f353f35,0x3f6dbec4,0xbf35bf35,0xbf6d3ec4,0x3f800000,0x3ec4bf6d,0xbf800000,0xbec43f6d,0xbf35bf35,0xbf6d3ec4,0x3f353f35,0x3f6dbec4,
0x3f80,0x3f6d3ec4,0xbf80,0xbf6dbec4,0x3f35bf35,0xbec4bf6d,0xbf353f35,0x3ec43f6d,0x80003f80,0x3f6dbec4,0x8000bf80,0xbf6d3ec4,
0xbf35bf35,0xbec43f6d,0x3f353f35,0x3ec4bf6d,0x3f800000,0xbec4bf6d,0xbf800000,0x3ec43f6d,0xbf353f35,0x3f6d3ec4,0x3f35bf35,0xbf6dbec4,
0x3f800000,0xbec4bf6d,0xbf800000,0x3ec43f6d,0xbf353f35,0x3f6d3ec4,0x3f35bf35,0xbf6dbec4,0xbf80,0xbf6d3ec4,0x3f80,0x3f6dbec4,
0x3f353f35,0x3ec4bf6d,0xbf35bf35,0xbec43f6d,0x80003f80,0x3ec4bf6d,0x8000bf80,0xbec43f6d,0xbf353f35,0x3f6dbec4,0x3f35bf35,0xbf6d3ec4,
0xbf800000,0x3f6d3ec4,0x3f800000,0xbf6dbec4,0xbf35bf35,0x3ec43f6d,0x3f353f35,0xbec4bf6d,0x3f800000,0xbf6dbec4,0xbf800000,0x3f6d3ec4,
0x3f353f35,0xbec4bf6d,0xbf35bf35,0x3ec43f6d,0x3f80,0x3ec4bf6d,0xbf80,0xbec43f6d,0xbf353f35,0x3f6dbec4,0x3f35bf35,0xbf6d3ec4,
0x80003f80,0x8000bf80,0x80003f80,0x8000bf80,0x80003f80,0x8000bf80,0x80003f80,0x8000bf80,0x80003f80,0x8000bf80,0x80003f80,0x8000bf80,
0x80003f80,0x8000bf80,0x80003f80,0x8000bf80,0x3f800000,0xbf800000,0x3f800000,0xbf800000,0x3f800000,0xbf800000,0x3f800000,0xbf800000,
0x3f800000,0xbf800000,0x3f800000,0xbf800000,0x3f800000,0xbf800000,0x3f800000,0xbf800000,0x80003f80,0xbf35bf35,0x80003f80,0xbf35bf35,
0x3f800000,0xbf353f35,0x3f800000,0xbf353f35,0x8000bf80,0x3f353f35,0x8000bf80,0x3f353f35,0xbf800000,0x3f35bf35,0xbf800000,0x3f35bf35,
0x3f800000,0xbf353f35,0x3f800000,0xbf353f35,0xbf80,0x3f353f35,0xbf80,0x3f353f35,0xbf800000,0x3f35bf35,0xbf800000,0x3f35bf35,
0x3f80,0xbf35bf35,0x3f80,0xbf35bf35,0x80003f80,0xbf800000,0x80003f80,0xbf800000,0x8000bf80,0x3f800000,0x8000bf80,0x3f800000,
0x80003f80,0xbf800000,0x80003f80,0xbf800000,0x8000bf80,0x3f800000,0x8000bf80,0x3f800000,0x3f800000,0x3f80,0x3f800000,0x3f80,
0xbf800000,0xbf80,0xbf800000,0xbf80,0x3f800000,0x3f80,0x3f800000,0x3f80,0xbf800000,0xbf80,0xbf800000,0xbf80,
0x80003f80,0xbf353f35,0x80003f80,0xbf353f35,0xbf800000,0xbf35bf35,0xbf800000,0xbf35bf35,0x8000bf80,0x3f35bf35,0x8000bf80,0x3f35bf35,
0x3f800000,0x3f353f35,0x3f800000,0x3f353f35,0x3f800000,0x3f353f35,0x3f800000,0x3f353f35,0x3f80,0xbf353f35,0x3f80,0xbf353f35,
0xbf800000,0xbf35bf35,0xbf800000,0xbf35bf35,0xbf80,0x3f35bf35,0xbf80,0x3f35bf35,0x80003f80,0xbec4bf6d,0x8000bf80,0x3ec43f6d,
0x3f353f35,0xbf6dbec4,0xbf35bf35,0x3f6d3ec4,0x3f800000,0xbf6d3ec4,0xbf800000,0x3f6dbec4,0x3f35bf35,0xbec43f6d,0xbf353f35,0x3ec4bf6d,
0x3f800000,0xbf6d3ec4,0xbf800000,0x3f6dbec4,0x3f35bf35,0xbec43f6d,0xbf353f35,0x3ec4bf6d,0xbf80,0x3ec43f6d,0x3f80,0xbec4bf6d,
0xbf35bf35,0x3f6d3ec4,0x3f353f35,0xbf6dbec4,0x80003f80,0xbf6dbec4,0x8000bf80,0x3f6d3ec4,0x3f35bf35,0x3ec43f6d,0xbf353f35,0xbec4bf6d,
0xbf800000,0x3ec4bf6d,0x3f800000,0xbec43f6d,0x3f353f35,0xbf6d3ec4,0xbf35bf35,0x3f6dbec4,0x3f800000,0xbec43f6d,0xbf800000,0x3ec4bf6d,
0xbf35bf35,0x3f6dbec4,0x3f353f35,0xbf6d3ec4,0x3f80,0xbf6dbec4,0xbf80,0x3f6d3ec4,0x3f35bf35,0x3ec43f6d,0xbf353f35,0xbec4bf6d,
0x80003f80,0xbf6d3ec4,0x8000bf80,0x3f6dbec4,0xbf35bf35,0x3ec4bf6d,0x3f353f35,0xbec43f6d,0x3f800000,0x3ec43f6d,0xbf800000,0xbec4bf6d,
0xbf353f35,0xbf6dbec4,0x3f35bf35,0x3f6d3ec4,0x3f800000,0x3ec43f6d,0xbf800000,0xbec4bf6d,0xbf353f35,0xbf6dbec4,0x3f35bf35,0x3f6d3ec4,
0xbf80,0x3f6dbec4,0x3f80,0xbf6d3ec4,0x3f353f35,0xbec43f6d,0xbf35bf35,0x3ec4bf6d,0x80003f80,0xbec43f6d,0x8000bf80,0x3ec4bf6d,
0xbf353f35,0xbf6d3ec4,0x3f35bf35,0x3f6dbec4,0xbf800000,0xbf6dbec4,0x3f800000,0x3f6d3ec4,0xbf35bf35,0xbec4bf6d,0x3f353f35,0x3ec43f6d,
0x3f800000,0x3f6d3ec4,0xbf800000,0xbf6dbec4,0x3f353f35,0x3ec43f6d,0xbf35bf35,0xbec4bf6d,0x3f80,0xbec43f6d,0xbf80,0x3ec4bf6d,
0xbf353f35,0xbf6d3ec4,0x3f35bf35,0x3f6dbec4,
};
constexpr int TB_F = 0, TB_E = 512, TB_P2 = 1024;

enum { C_EP = 0, C_Z1 = 32, C_Z2 = 96, C_H3 = 128, C_U = 160, C_X = 288, C_TOTAL = 512 };
struct Scratch {
  unsigned cnt[C_TOTAL];
  uint32_t moda[8 * 2 * D_];
  uint32_t mod[4 * D_ + 256];
  uint32_t z1[120 * 5120];
  uint32_t z2[128 * 4800];
  uint8_t h3[32 * 18 * 4096];
  uint8_t u[72 * D_ * 128];
};
__device__ __align__(1024) Scratch g_s;

#define HOLDA 5
#define GOAT 0
#define H3W 0
#define X1K 10
#define PEEK 1
#ifndef NV1
#define NV1 12
#endif
#ifndef NV2
#define NV2 20
#endif
#define GDEP 0
#define TRK0 50
#define W0N 3
#define TRKC 350
#define HD1 150
#define STRESS 0
#define KNOB0 0

#define FAILCNT(k) do {} while (0)
#define CK(k) do {} while (0)
#define CKX(k) do {} while (0)
#define TS(k) do {} while (0)
#define TSC(k) do {} while (0)
struct Maps { CUtensorMap z1, z2[2], w1a, w1b, h3, w2, wf[4], wm; };
struct Params {
  const __nv_bfloat16 *x, *c, *wmod;
  Scratch* s;
  const uint4* tab;
  const __nv_bfloat16 *wr, *wi, *w1, *w2, *b1, *b2;
  uint32_t* out;
};

__device__ __forceinline__ uint32_t smem_u32(const void* p) { return (uint32_t)__cvta_generic_to_shared(p); }
__device__ __forceinline__ void mbar_init(uint32_t b, int c) { asm volatile("mbarrier.init.shared::cta.b64 [%0], %1;" ::"r"(b), "r"(c)); }
__device__ __forceinline__ void mbar_expect(uint32_t b, int bytes) { asm volatile("mbarrier.arrive.expect_tx.shared::cta.b64 _, [%0], %1;" ::"r"(b), "r"(bytes) : "memory"); }
__device__ __forceinline__ void mbar_arrive(uint32_t b) { asm volatile("mbarrier.arrive.shared::cta.b64 _, [%0];" ::"r"(b) : "memory"); }
#define MBAR_WAIT(SEM)                                                                                                         \
  asm volatile("{\n.reg .pred p;\n.reg .u32 it;\nmov.u32 it, 0;\nW:\nmbarrier.try_wait.parity" SEM ".shared::cta.b64 p, [%0], %1;\n" \
               "@p bra.uni D;\nadd.u32 it, it, 1;\nsetp.lt.u32 p, it, 0x400000;\n@p bra.uni W;\ntrap;\nD:\n}" ::"r"(b), "r"(ph) : "memory")
__device__ __forceinline__ void mbar_wait(uint32_t b, int ph) { MBAR_WAIT(""); }
__device__ __forceinline__ uint32_t mbar_test(uint32_t b, int ph) {
  uint32_t ok;
  asm volatile("{\n.reg .pred p;\nmbarrier.test_wait.parity.shared::cta.b64 p, [%1], %2;\nselp.u32 %0, 1, 0, p;\n}\n" : "=r"(ok) : "r"(b), "r"(ph) : "memory");
  return ok;
}
__device__ __forceinline__ void tma2d(uint32_t dst, const CUtensorMap* m, int c0, int c1, uint32_t bar) {
  asm volatile("cp.async.bulk.tensor.2d.shared::cluster.global.mbarrier::complete_tx::bytes [%0], [%1, {%3, %4}], [%2];" ::"r"(dst), "l"(m), "r"(bar), "r"(c0), "r"(c1) : "memory");
}
__device__ __forceinline__ uint64_t pol_ef() { uint64_t p; asm("createpolicy.fractional.L2::evict_first.b64 %0, 1.0;" : "=l"(p)); return p; }
__device__ __forceinline__ void tma3d_ef(uint32_t dst, const CUtensorMap* m, int c1, int c2, uint32_t bar) {
  asm volatile("cp.async.bulk.tensor.3d.shared::cluster.global.mbarrier::complete_tx::bytes.L2::cache_hint [%0], [%1, {%3, %4, %5}], [%2], %6;" ::"r"(dst), "l"(m), "r"(bar), "r"(0), "r"(c1), "r"(c2), "l"(pol_ef()) : "memory");
}
__device__ __forceinline__ void tma4d_ef(uint32_t dst, const CUtensorMap* m, int c1, int c2, int c3, uint32_t bar) {
  asm volatile("cp.async.bulk.tensor.4d.shared::cluster.global.mbarrier::complete_tx::bytes.L2::cache_hint [%0], [%1, {%3, %7, %4, %5}], [%2], %6;" ::"r"(dst), "l"(m), "r"(bar), "r"(0), "r"(c2), "r"(c3), "l"(pol_ef()), "r"(c1) : "memory");
}
__device__ __forceinline__ void bulk_ld(uint32_t dst, const void* src, int bytes, uint32_t bar) {
  asm volatile("cp.async.bulk.shared::cluster.global.mbarrier::complete_tx::bytes [%0], [%1], %2, [%3];" ::"r"(dst), "l"(src), "r"(bytes), "r"(bar) : "memory");
}
__device__ __forceinline__ void bulk_st(void* dst, uint32_t src, int bytes) {
  asm volatile("cp.async.bulk.global.shared::cta.bulk_group [%0], [%1], %2;" ::"l"(dst), "r"(src), "r"(bytes) : "memory");
}
__device__ __forceinline__ void tma_st2d(const CUtensorMap* m, uint32_t src, int c0, int c1) {
  asm volatile("cp.async.bulk.tensor.2d.global.shared::cta.bulk_group [%0, {%2, %3}], [%1];" ::"l"(m), "r"(src), "r"(c0), "r"(c1) : "memory");
}
__device__ __forceinline__ void tma_st3d(const CUtensorMap* m, uint32_t src, int c0, int c1, int c2) {
  asm volatile("cp.async.bulk.tensor.3d.global.shared::cta.bulk_group [%0, {%2, %3, %4}], [%1];" ::"l"(m), "r"(src), "r"(c0), "r"(c1), "r"(c2) : "memory");
}
__device__ __forceinline__ void bulk_commit_wait_read() {
  asm volatile("cp.async.bulk.commit_group;" ::: "memory");
  asm volatile("cp.async.bulk.wait_group.read 0;" ::: "memory");
}
__device__ __forceinline__ void bulk_commit_wait() {
  asm volatile("cp.async.bulk.commit_group;" ::: "memory");
  asm volatile("cp.async.bulk.wait_group 0;" ::: "memory");
}
__device__ __forceinline__ void prefetch_l2(const void* p, int bytes) {
  asm volatile("cp.async.bulk.prefetch.L2.global [%0], %1;" ::"l"(p), "r"(bytes) : "memory");
}
__device__ __forceinline__ void wg_fence() { asm volatile("wgmma.fence.sync.aligned;" ::: "memory"); }
__device__ __forceinline__ void wg_commit() { asm volatile("wgmma.commit_group.sync.aligned;" ::: "memory"); }
template <int N> __device__ __forceinline__ void wg_wait() { asm volatile("wgmma.wait_group.sync.aligned %0;" ::"n"(N) : "memory"); }
template <int N> __device__ __forceinline__ void reg_fence(float (&d)[N]) {
#pragma unroll
  for (int i = 0; i < N; i++) asm volatile("" : "+f"(d[i])::"memory");
}
__device__ __forceinline__ void fence_async_smem() { asm volatile("fence.proxy.async.shared::cta;" ::: "memory"); }
__device__ __forceinline__ void fence_async_glb() { asm volatile("fence.proxy.async.global;" ::: "memory"); }
__device__ __forceinline__ uint32_t ld_rlx(const void* p) { uint32_t v; asm volatile("ld.relaxed.gpu.global.b32 %0, [%1];" : "=r"(v) : "l"(p) : "memory"); return v; }
__device__ __forceinline__ uint2 ld_rlx2(const void* p) { uint2 v; asm volatile("ld.relaxed.gpu.global.v2.b32 {%0,%1}, [%2];" : "=r"(v.x), "=r"(v.y) : "l"(p) : "memory"); return v; }
__device__ __forceinline__ uint4 ld_rlx4(const void* p) { uint4 v; asm volatile("ld.relaxed.gpu.global.v4.b32 {%0,%1,%2,%3}, [%4];" : "=r"(v.x), "=r"(v.y), "=r"(v.z), "=r"(v.w) : "l"(p) : "memory"); return v; }
__device__ __forceinline__ uint32_t ld_nc(const void* p) { uint32_t v; asm volatile("ld.global.nc.L1::no_allocate.b32 %0, [%1];" : "=r"(v) : "l"(p) : "memory"); return v; }
__device__ __forceinline__ uint4 ld_nc4(const void* p) { uint4 v; asm volatile("ld.global.nc.v4.b32 {%0,%1,%2,%3}, [%4];" : "=r"(v.x), "=r"(v.y), "=r"(v.z), "=r"(v.w) : "l"(p) : "memory"); return v; }
__device__ __forceinline__ uint32_t lds(uint32_t a) { uint32_t v; asm volatile("ld.shared.b32 %0, [%1];" : "=r"(v) : "r"(a) : "memory"); return v; }
__device__ __forceinline__ uint2 lds2(uint32_t a) { uint2 v; asm volatile("ld.shared.v2.b32 {%0,%1}, [%2];" : "=r"(v.x), "=r"(v.y) : "r"(a) : "memory"); return v; }
__device__ __forceinline__ void lds2_if(int on, uint2& v, uint32_t a) { asm volatile("{\n.reg .pred p;\nsetp.ne.u32 p, %3, 0;\n@p ld.shared.v2.b32 {%0,%1}, [%2];\n}" : "+r"(v.x), "+r"(v.y) : "r"(a), "r"(on) : "memory"); }
__device__ __forceinline__ uint4 lds4(uint32_t a) { uint4 v; asm volatile("ld.shared.v4.b32 {%0,%1,%2,%3}, [%4];" : "=r"(v.x), "=r"(v.y), "=r"(v.z), "=r"(v.w) : "r"(a) : "memory"); return v; }
__device__ __forceinline__ float lds_bf(uint32_t a) { uint32_t v; asm volatile("ld.shared.u16 %0, [%1];" : "=r"(v) : "r"(a) : "memory"); return __uint_as_float(v << 16); }
__device__ __forceinline__ void sts(uint32_t a, uint32_t v) { asm volatile("st.shared.b32 [%0], %1;" ::"r"(a), "r"(v) : "memory"); }
__device__ __forceinline__ void sts2(uint32_t a, uint32_t v0, uint32_t v1) { asm volatile("st.shared.v2.b32 [%0], {%1,%2};" ::"r"(a), "r"(v0), "r"(v1) : "memory"); }
__device__ __forceinline__ void sts4(uint32_t a, uint32_t v0, uint32_t v1, uint32_t v2, uint32_t v3) { asm volatile("st.shared.v4.b32 [%0], {%1,%2,%3,%4};" ::"r"(a), "r"(v0), "r"(v1), "r"(v2), "r"(v3) : "memory"); }
__device__ __forceinline__ void bar_sync(int id, int n) { asm volatile("bar.sync %0, %1;" ::"r"(id), "r"(n) : "memory"); }
__device__ __forceinline__ void bar_arrive(int id, int n) { asm volatile("bar.arrive %0, %1;" ::"r"(id), "r"(n) : "memory"); }
__device__ __forceinline__ void red_add(unsigned* p, unsigned v) { asm volatile("red.relaxed.gpu.global.add.u32 [%0], %1;" ::"l"(p), "r"(v) : "memory"); }
__device__ __forceinline__ bool any(bool p) { return __any_sync(0xffffffffu, p); }
__device__ __forceinline__ void pause(unsigned clks) {
  asm volatile("{\n.reg .pred p;\n.reg .u32 a, b;\nmov.u32 a, %%clock;\nW:\nmov.u32 b, %%clock;\nsub.u32 b, b, a;\nsetp.lt.s32 p, b, %0;\n@p bra.uni W;\n}" ::"r"(clks) : "memory");
}
__device__ __forceinline__ void red_bf16x8(uint32_t* p, uint32_t a, uint32_t b, uint32_t c, uint32_t d) {
  asm volatile("red.relaxed.gpu.global.add.noftz.v4.bf16x2 [%0], {%1,%2,%3,%4};" ::"l"(p), "r"(a), "r"(b), "r"(c), "r"(d) : "memory");
}
__device__ __forceinline__ void red_bf16x4(uint32_t* p, uint32_t a, uint32_t b) {
  asm volatile("red.relaxed.gpu.global.add.noftz.v2.bf16x2 [%0], {%1,%2};" ::"l"(p), "r"(a), "r"(b) : "memory");
}
constexpr int SPIN_MAX = 1 << 20;
__device__ __forceinline__ uint32_t ld_acq(const void* p) { uint32_t v; asm volatile("ld.acquire.gpu.global.b32 %0, [%1];" : "=r"(v) : "l"(p) : "memory"); return v; }
template <bool ACQ = false> __device__ __forceinline__ void wait_cnt(const unsigned* p, unsigned target) {
  int it = 0;
  while (any((int)((ACQ ? ld_acq(p) : ld_rlx(p)) - target) < 0) && ++it < SPIN_MAX) {}
}
__device__ __forceinline__ uint32_t pack_bf16(float lo, float hi) { uint32_t r; asm("cvt.rn.bf16x2.f32 %0, %1, %2;" : "=r"(r) : "f"(hi), "f"(lo)); return r; }
__device__ __forceinline__ float bf_lo(uint32_t v) { return __uint_as_float(v << 16); }
__device__ __forceinline__ float bf_hi(uint32_t v) { return __uint_as_float(v & 0xffff0000u); }
__device__ __forceinline__ uint32_t hadd2(uint32_t a, uint32_t b) { uint32_t r; asm("add.rn.bf16x2 %0, %1, %2;" : "=r"(r) : "r"(a), "r"(b)); return r; }
__device__ __forceinline__ uint32_t hmul2(uint32_t a, uint32_t b) { uint32_t r; asm("mul.rn.bf16x2 %0, %1, %2;" : "=r"(r) : "r"(a), "r"(b)); return r; }
__device__ __forceinline__ uint32_t hfma2(uint32_t a, uint32_t b, uint32_t c) { uint32_t r; asm("fma.rn.bf16x2 %0, %1, %2, %3;" : "=r"(r) : "r"(a), "r"(b), "r"(c)); return r; }
__device__ __forceinline__ float rbf(float x) { uint32_t r; asm("cvt.rn.bf16x2.f32 %0, %1, %2;" : "=r"(r) : "f"(x), "f"(0.0f)); return __uint_as_float(r); }
__device__ __forceinline__ void stmatrix4(uint32_t a, uint32_t r0, uint32_t r1, uint32_t r2, uint32_t r3) {
  asm volatile("stmatrix.sync.aligned.m8n8.x4.shared.b16 [%0], {%1,%2,%3,%4};" ::"r"(a), "r"(r0), "r"(r1), "r"(r2), "r"(r3) : "memory");
}
__device__ __forceinline__ void stmatrix2(uint32_t a, uint32_t r0, uint32_t r1) {
  asm volatile("stmatrix.sync.aligned.m8n8.x2.shared.b16 [%0], {%1,%2};" ::"r"(a), "r"(r0), "r"(r1) : "memory");
}
__device__ __forceinline__ uint32_t movm(uint32_t a) { uint32_t r; asm("movmatrix.sync.aligned.m8n8.trans.b16 %0, %1;" : "=r"(r) : "r"(a)); return r; }
template <bool ACC> __device__ __forceinline__ void mma16(float* d, uint32_t a0, uint32_t a1, uint32_t a2, uint32_t a3, uint32_t b0, uint32_t b1) {
  if (ACC) asm("mma.sync.aligned.m16n8k16.row.col.f32.bf16.bf16.f32 {%0,%1,%2,%3}, {%4,%5,%6,%7}, {%8,%9}, {%0,%1,%2,%3};"
               : "+f"(d[0]), "+f"(d[1]), "+f"(d[2]), "+f"(d[3]) : "r"(a0), "r"(a1), "r"(a2), "r"(a3), "r"(b0), "r"(b1));
  else asm("mma.sync.aligned.m16n8k16.row.col.f32.bf16.bf16.f32 {%0,%1,%2,%3}, {%4,%5,%6,%7}, {%8,%9}, {%10,%10,%10,%10};"
           : "=f"(d[0]), "=f"(d[1]), "=f"(d[2]), "=f"(d[3]) : "r"(a0), "r"(a1), "r"(a2), "r"(a3), "r"(b0), "r"(b1), "f"(0.f));
}
__device__ __forceinline__ uint32_t pin(uint32_t v) { uint32_t r; asm volatile("shfl.sync.bfly.b32 %0, %1, 0, 31, 0xffffffff;" : "=r"(r) : "r"(v)); return r; }
template <class T> __device__ __forceinline__ T* pin(T* p) {
  const uint64_t a = reinterpret_cast<uint64_t>(p);
  return reinterpret_cast<T*>((uint64_t)pin((uint32_t)a) | ((uint64_t)pin((uint32_t)(a >> 32)) << 32));
}
__device__ __forceinline__ uint32_t upin(uint32_t v) { return __shfl_sync(0xffffffffu, v, 0); }
template <class T> __device__ __forceinline__ T* upin(T* p) {
  const uint64_t a = reinterpret_cast<uint64_t>(p);
  return reinterpret_cast<T*>((uint64_t)upin((uint32_t)a) | ((uint64_t)upin((uint32_t)(a >> 32)) << 32));
}
__device__ __forceinline__ bool elect() {
  uint32_t p;
  asm volatile("{\n.reg .pred P;\nelect.sync _|P, 0xffffffff;\nselp.u32 %0, 1, 0, P;\n}" : "=r"(p));
  return p;
}
__device__ __forceinline__ uint32_t set_tag(uint32_t w, uint32_t tag) { uint32_t r; asm("lop3.b32 %0, %1, 0xfffffffe, %2, 0xea;" : "=r"(r) : "r"(w), "r"(tag)); return r; }
__device__ __forceinline__ uint32_t bitsel(uint32_t w, uint32_t m, uint32_t o) { uint32_t r; asm("lop3.b32 %0, %1, %2, %3, 0xe2;" : "=r"(r) : "r"(w), "r"(m), "r"(o)); return r; }
__device__ __forceinline__ uint32_t or3(uint32_t a, uint32_t b, uint32_t c) { uint32_t r; asm("lop3.b32 %0, %1, %2, %3, 0xfe;" : "=r"(r) : "r"(a), "r"(b), "r"(c)); return r; }
__device__ __forceinline__ uint32_t diff2(uint32_t a, uint32_t b, uint32_t tag) { uint32_t r; asm("lop3.b32 %0, %1, %2, %3, 0x7e;" : "=r"(r) : "r"(a), "r"(b), "r"(tag)); return r; }
__device__ __forceinline__ float2 cmul(float2 a, float2 b) { return make_float2(a.x * b.x - a.y * b.y, a.x * b.y + a.y * b.x); }

template<int TB> __device__ __forceinline__ void wgmma_ss_160_0(float (&d)[96], uint32_t al, uint32_t ah, uint32_t bl, uint32_t bh) {
  asm volatile("{\n.reg .b64 da, db;\nmov.b64 da, {%80, %81};\nmov.b64 db, {%82, %83};\n"
    "wgmma.mma_async.sync.aligned.m64n160k16.f32.bf16.bf16 {%0,%1,%2,%3,%4,%5,%6,%7,%8,%9,%10,%11,%12,%13,%14,%15,%16,%17,%18,%19,%20,%21,%22,%23,%24,%25,%26,%27,%28,%29,%30,%31,%32,%33,%34,%35,%36,%37,%38,%39,%40,%41,%42,%43,%44,%45,%46,%47,%48,%49,%50,%51,%52,%53,%54,%55,%56,%57,%58,%59,%60,%61,%62,%63,%64,%65,%66,%67,%68,%69,%70,%71,%72,%73,%74,%75,%76,%77,%78,%79}, da, db, 1, 1, 1, 1, %84;\n}\n"
    : "+f"(d[0]),"+f"(d[1]),"+f"(d[2]),"+f"(d[3]),"+f"(d[4]),"+f"(d[5]),"+f"(d[6]),"+f"(d[7]),"+f"(d[8]),"+f"(d[9]),"+f"(d[10]),"+f"(d[11]),"+f"(d[12]),"+f"(d[13]),"+f"(d[14]),"+f"(d[15]),"+f"(d[16]),"+f"(d[17]),"+f"(d[18]),"+f"(d[19]),"+f"(d[20]),"+f"(d[21]),"+f"(d[22]),"+f"(d[23]),"+f"(d[24]),"+f"(d[25]),"+f"(d[26]),"+f"(d[27]),"+f"(d[28]),"+f"(d[29]),"+f"(d[30]),"+f"(d[31]),"+f"(d[32]),"+f"(d[33]),"+f"(d[34]),"+f"(d[35]),"+f"(d[36]),"+f"(d[37]),"+f"(d[38]),"+f"(d[39]),"+f"(d[40]),"+f"(d[41]),"+f"(d[42]),"+f"(d[43]),"+f"(d[44]),"+f"(d[45]),"+f"(d[46]),"+f"(d[47]),"+f"(d[48]),"+f"(d[49]),"+f"(d[50]),"+f"(d[51]),"+f"(d[52]),"+f"(d[53]),"+f"(d[54]),"+f"(d[55]),"+f"(d[56]),"+f"(d[57]),"+f"(d[58]),"+f"(d[59]),"+f"(d[60]),"+f"(d[61]),"+f"(d[62]),"+f"(d[63]),"+f"(d[64]),"+f"(d[65]),"+f"(d[66]),"+f"(d[67]),"+f"(d[68]),"+f"(d[69]),"+f"(d[70]),"+f"(d[71]),"+f"(d[72]),"+f"(d[73]),"+f"(d[74]),"+f"(d[75]),"+f"(d[76]),"+f"(d[77]),"+f"(d[78]),"+f"(d[79])
    : "r"(al), "r"(ah), "r"(bl), "r"(bh), "n"(TB));
}
template<int TB> __device__ __forceinline__ void wgmma_ss_144_0(float (&d)[96], uint32_t al, uint32_t ah, uint32_t bl, uint32_t bh) {
  asm volatile("{\n.reg .b64 da, db;\nmov.b64 da, {%72, %73};\nmov.b64 db, {%74, %75};\n"
    "wgmma.mma_async.sync.aligned.m64n144k16.f32.bf16.bf16 {%0,%1,%2,%3,%4,%5,%6,%7,%8,%9,%10,%11,%12,%13,%14,%15,%16,%17,%18,%19,%20,%21,%22,%23,%24,%25,%26,%27,%28,%29,%30,%31,%32,%33,%34,%35,%36,%37,%38,%39,%40,%41,%42,%43,%44,%45,%46,%47,%48,%49,%50,%51,%52,%53,%54,%55,%56,%57,%58,%59,%60,%61,%62,%63,%64,%65,%66,%67,%68,%69,%70,%71}, da, db, 1, 1, 1, 1, %76;\n}\n"
    : "+f"(d[0]),"+f"(d[1]),"+f"(d[2]),"+f"(d[3]),"+f"(d[4]),"+f"(d[5]),"+f"(d[6]),"+f"(d[7]),"+f"(d[8]),"+f"(d[9]),"+f"(d[10]),"+f"(d[11]),"+f"(d[12]),"+f"(d[13]),"+f"(d[14]),"+f"(d[15]),"+f"(d[16]),"+f"(d[17]),"+f"(d[18]),"+f"(d[19]),"+f"(d[20]),"+f"(d[21]),"+f"(d[22]),"+f"(d[23]),"+f"(d[24]),"+f"(d[25]),"+f"(d[26]),"+f"(d[27]),"+f"(d[28]),"+f"(d[29]),"+f"(d[30]),"+f"(d[31]),"+f"(d[32]),"+f"(d[33]),"+f"(d[34]),"+f"(d[35]),"+f"(d[36]),"+f"(d[37]),"+f"(d[38]),"+f"(d[39]),"+f"(d[40]),"+f"(d[41]),"+f"(d[42]),"+f"(d[43]),"+f"(d[44]),"+f"(d[45]),"+f"(d[46]),"+f"(d[47]),"+f"(d[48]),"+f"(d[49]),"+f"(d[50]),"+f"(d[51]),"+f"(d[52]),"+f"(d[53]),"+f"(d[54]),"+f"(d[55]),"+f"(d[56]),"+f"(d[57]),"+f"(d[58]),"+f"(d[59]),"+f"(d[60]),"+f"(d[61]),"+f"(d[62]),"+f"(d[63]),"+f"(d[64]),"+f"(d[65]),"+f"(d[66]),"+f"(d[67]),"+f"(d[68]),"+f"(d[69]),"+f"(d[70]),"+f"(d[71])
    : "r"(al), "r"(ah), "r"(bl), "r"(bh), "n"(TB));
}
template<int TB> __device__ __forceinline__ void wgmma_ss_96_0(float (&d)[96], uint32_t al, uint32_t ah, uint32_t bl, uint32_t bh) {
  asm volatile("{\n.reg .b64 da, db;\nmov.b64 da, {%48, %49};\nmov.b64 db, {%50, %51};\n"
    "wgmma.mma_async.sync.aligned.m64n96k16.f32.bf16.bf16 {%0,%1,%2,%3,%4,%5,%6,%7,%8,%9,%10,%11,%12,%13,%14,%15,%16,%17,%18,%19,%20,%21,%22,%23,%24,%25,%26,%27,%28,%29,%30,%31,%32,%33,%34,%35,%36,%37,%38,%39,%40,%41,%42,%43,%44,%45,%46,%47}, da, db, 1, 1, 1, 1, %52;\n}\n"
    : "+f"(d[0]),"+f"(d[1]),"+f"(d[2]),"+f"(d[3]),"+f"(d[4]),"+f"(d[5]),"+f"(d[6]),"+f"(d[7]),"+f"(d[8]),"+f"(d[9]),"+f"(d[10]),"+f"(d[11]),"+f"(d[12]),"+f"(d[13]),"+f"(d[14]),"+f"(d[15]),"+f"(d[16]),"+f"(d[17]),"+f"(d[18]),"+f"(d[19]),"+f"(d[20]),"+f"(d[21]),"+f"(d[22]),"+f"(d[23]),"+f"(d[24]),"+f"(d[25]),"+f"(d[26]),"+f"(d[27]),"+f"(d[28]),"+f"(d[29]),"+f"(d[30]),"+f"(d[31]),"+f"(d[32]),"+f"(d[33]),"+f"(d[34]),"+f"(d[35]),"+f"(d[36]),"+f"(d[37]),"+f"(d[38]),"+f"(d[39]),"+f"(d[40]),"+f"(d[41]),"+f"(d[42]),"+f"(d[43]),"+f"(d[44]),"+f"(d[45]),"+f"(d[46]),"+f"(d[47])
    : "r"(al), "r"(ah), "r"(bl), "r"(bh), "n"(TB));
}
template<int TB> __device__ __forceinline__ void wgmma_ss_96_48(float (&d)[96], uint32_t al, uint32_t ah, uint32_t bl, uint32_t bh) {
  asm volatile("{\n.reg .b64 da, db;\nmov.b64 da, {%48, %49};\nmov.b64 db, {%50, %51};\n"
    "wgmma.mma_async.sync.aligned.m64n96k16.f32.bf16.bf16 {%0,%1,%2,%3,%4,%5,%6,%7,%8,%9,%10,%11,%12,%13,%14,%15,%16,%17,%18,%19,%20,%21,%22,%23,%24,%25,%26,%27,%28,%29,%30,%31,%32,%33,%34,%35,%36,%37,%38,%39,%40,%41,%42,%43,%44,%45,%46,%47}, da, db, 1, 1, 1, 1, %52;\n}\n"
    : "+f"(d[48]),"+f"(d[49]),"+f"(d[50]),"+f"(d[51]),"+f"(d[52]),"+f"(d[53]),"+f"(d[54]),"+f"(d[55]),"+f"(d[56]),"+f"(d[57]),"+f"(d[58]),"+f"(d[59]),"+f"(d[60]),"+f"(d[61]),"+f"(d[62]),"+f"(d[63]),"+f"(d[64]),"+f"(d[65]),"+f"(d[66]),"+f"(d[67]),"+f"(d[68]),"+f"(d[69]),"+f"(d[70]),"+f"(d[71]),"+f"(d[72]),"+f"(d[73]),"+f"(d[74]),"+f"(d[75]),"+f"(d[76]),"+f"(d[77]),"+f"(d[78]),"+f"(d[79]),"+f"(d[80]),"+f"(d[81]),"+f"(d[82]),"+f"(d[83]),"+f"(d[84]),"+f"(d[85]),"+f"(d[86]),"+f"(d[87]),"+f"(d[88]),"+f"(d[89]),"+f"(d[90]),"+f"(d[91]),"+f"(d[92]),"+f"(d[93]),"+f"(d[94]),"+f"(d[95])
    : "r"(al), "r"(ah), "r"(bl), "r"(bh), "n"(TB));
}
__device__ __forceinline__ void wgmma_rs_72(float (&d)[36], uint32_t a0, uint32_t a1, uint32_t a2, uint32_t a3, uint32_t bl, uint32_t bh, int sd) {
  asm volatile("{\n.reg .pred p;\n.reg .b64 db;\nsetp.ne.b32 p, %42, 0;\nmov.b64 db, {%40, %41};\n"
    "wgmma.mma_async.sync.aligned.m64n72k16.f32.bf16.bf16 {%0,%1,%2,%3,%4,%5,%6,%7,%8,%9,%10,%11,%12,%13,%14,%15,%16,%17,%18,%19,%20,%21,%22,%23,%24,%25,%26,%27,%28,%29,%30,%31,%32,%33,%34,%35}, {%36,%37,%38,%39}, db, p, 1, 1, 1;\n}\n"
    : "+f"(d[0]),"+f"(d[1]),"+f"(d[2]),"+f"(d[3]),"+f"(d[4]),"+f"(d[5]),"+f"(d[6]),"+f"(d[7]),"+f"(d[8]),"+f"(d[9]),"+f"(d[10]),"+f"(d[11]),"+f"(d[12]),"+f"(d[13]),"+f"(d[14]),"+f"(d[15]),"+f"(d[16]),"+f"(d[17]),"+f"(d[18]),"+f"(d[19]),"+f"(d[20]),"+f"(d[21]),"+f"(d[22]),"+f"(d[23]),"+f"(d[24]),"+f"(d[25]),"+f"(d[26]),"+f"(d[27]),"+f"(d[28]),"+f"(d[29]),"+f"(d[30]),"+f"(d[31]),"+f"(d[32]),"+f"(d[33]),"+f"(d[34]),"+f"(d[35])
    : "r"(a0), "r"(a1), "r"(a2), "r"(a3), "r"(bl), "r"(bh), "r"(sd));
}
__device__ __forceinline__ void wgmma_rs_48(float (&d)[24], uint32_t a0, uint32_t a1, uint32_t a2, uint32_t a3, uint32_t bl, uint32_t bh, int sd) {
  asm volatile("{\n.reg .pred p;\n.reg .b64 db;\nsetp.ne.b32 p, %30, 0;\nmov.b64 db, {%28, %29};\n"
    "wgmma.mma_async.sync.aligned.m64n48k16.f32.bf16.bf16 {%0,%1,%2,%3,%4,%5,%6,%7,%8,%9,%10,%11,%12,%13,%14,%15,%16,%17,%18,%19,%20,%21,%22,%23}, {%24,%25,%26,%27}, db, p, 1, 1, 1;\n}\n"
    : "+f"(d[0]),"+f"(d[1]),"+f"(d[2]),"+f"(d[3]),"+f"(d[4]),"+f"(d[5]),"+f"(d[6]),"+f"(d[7]),"+f"(d[8]),"+f"(d[9]),"+f"(d[10]),"+f"(d[11]),"+f"(d[12]),"+f"(d[13]),"+f"(d[14]),"+f"(d[15]),"+f"(d[16]),"+f"(d[17]),"+f"(d[18]),"+f"(d[19]),"+f"(d[20]),"+f"(d[21]),"+f"(d[22]),"+f"(d[23])
    : "r"(a0), "r"(a1), "r"(a2), "r"(a3), "r"(bl), "r"(bh), "r"(sd));
}
template<int N,int OFF,int TB> __device__ __forceinline__ void wgmma_ss(float (&d)[96], uint32_t al, uint32_t ah, uint32_t bl, uint32_t bh) {
  if constexpr (N==160 && OFF==0) wgmma_ss_160_0<TB>(d, al, ah, bl, bh);
  else if constexpr (N==144 && OFF==0) wgmma_ss_144_0<TB>(d, al, ah, bl, bh);
  else if constexpr (N==96 && OFF==0) wgmma_ss_96_0<TB>(d, al, ah, bl, bh);
  else if constexpr (N==96 && OFF==48) wgmma_ss_96_48<TB>(d, al, ah, bl, bh);
}

__device__ __forceinline__ void dft3(float2& a, float2& b, float2& c) {
  const float s = 0.86602540378443864676f;
  float2 t = make_float2(b.x + c.x, b.y + c.y), d = make_float2(b.x - c.x, b.y - c.y);
  float2 m = make_float2(fmaf(-0.5f, t.x, a.x), fmaf(-0.5f, t.y, a.y));
  a = make_float2(a.x + t.x, a.y + t.y);
  b = make_float2(fmaf(s, d.y, m.x), fmaf(-s, d.x, m.y));
  c = make_float2(fmaf(-s, d.y, m.x), fmaf(s, d.x, m.y));
}
__device__ __forceinline__ void dft9(float2 (&x)[9]) {
  const float2 w1 = make_float2(0.76604444311897803520f, -0.64278760968653932632f);
  const float2 w2 = make_float2(0.17364817766693034885f, -0.98480775301220805937f);
  const float2 w4 = make_float2(-0.93969262078590838405f, -0.34202014332566873304f);
  dft3(x[0], x[3], x[6]); dft3(x[1], x[4], x[7]); dft3(x[2], x[5], x[8]);
  x[4] = cmul(x[4], w1); x[7] = cmul(x[7], w2); x[5] = cmul(x[5], w2); x[8] = cmul(x[8], w4);
  dft3(x[0], x[1], x[2]); dft3(x[3], x[4], x[5]); dft3(x[6], x[7], x[8]);
  float2 t;
  t = x[1]; x[1] = x[3]; x[3] = t;
  t = x[2]; x[2] = x[6]; x[6] = t;
  t = x[5]; x[5] = x[7]; x[7] = t;
}

__device__ __forceinline__ uint32_t* mod_ptr(Scratch* sc, int u, int t128) {
  const int i = t128 & 15;
  return u < 72 ? sc->moda + (t128 >> 4) * (2 * D_) + 16 * u + 2 * (i & 7) + (i >> 3) : sc->mod + 16 * (u - 72) + i;
}
__device__ __forceinline__ void mod_unit(Scratch* sc, int u, int t128, uint32_t sw_, uint32_t bar, int ph, uint32_t rb, uint32_t tag) {
  const int w = t128 >> 5, l = t128 & 31;
  uint32_t b[18];
#pragma unroll
  for (int i = 0; i < 18; i++) b[i] = lds(red + 512 + (72 * w + 4 * i + (l & 3)) * 4);
  const uint32_t sa = pin(sw_ + (144 * w + (l & 7) + 8 * (l >> 4)) * 32 + (((l >> 3) ^ (l >> 2)) & 1) * 16);
  const uint32_t sr = pin(rb + (l >> 2) * 16 + w * 4);
  uint32_t* const dst = pin(mod_ptr(sc, u, t128));
  const int kind = u / 36;
  const float mul = __uint_as_float(pin(__float_as_uint(kind == 0 ? 16.0f : 1.0f))), add = __uint_as_float(pin(__float_as_uint(kind == 1 || kind == 4 ? 1.0f : 0.0f)));
  mbar_wait(bar, ph);
  if (t128 == 0 && u < 72) TS(10);
  float d[3][4];
#pragma unroll
  for (int i = 0; i < 9; i++) {
    uint32_t a0, a1, a2, a3;
    asm volatile("ldmatrix.sync.aligned.m8n8.x4.trans.shared.b16 {%0,%1,%2,%3}, [%4];" : "=r"(a0), "=r"(a1), "=r"(a2), "=r"(a3) : "r"(sa + i * 512) : "memory");
    if (i < 3) mma16<false>(d[i], a0, a1, a2, a3, b[2 * i], b[2 * i + 1]);
    else mma16<true>(d[i % 3], a0, a1, a2, a3, b[2 * i], b[2 * i + 1]);
  }
  if ((l & 3) == 0) { sts(sr, __float_as_uint(d[0][0] + d[1][0] + d[2][0])); sts(sr + 128, __float_as_uint(d[0][2] + d[1][2] + d[2][2])); }
  bar_sync(4, 128);
  const uint4 v = lds4(rb + (l & 15) * 16);
  const float m = rbf(fmaf(rbf((__uint_as_float(v.x) + __uint_as_float(v.y)) + (__uint_as_float(v.z) + __uint_as_float(v.w))), mul, add));
  if (u < 72 || t128 < 16) *dst = __float_as_uint(m) | tag;
}

__device__ __forceinline__ float rsq(float x) { float r; asm("rsqrt.approx.ftz.f32 %0, %1;" : "=f"(r) : "f"(x)); return r; }
__device__ __forceinline__ void ln_stats2(const float (&a)[18], const float (&b)[18], float sc, float& oa, float& ra, float& ob, float& rb) {
  float v[4] = {0.f, 0.f, 0.f, 0.f}, w[4] = {0.f, 0.f, 0.f, 0.f};
#pragma unroll
  for (int i = 0; i < 18; i += 2) {
    v[0] += a[i]; v[1] = fmaf(a[i], a[i], v[1]); v[2] += b[i]; v[3] = fmaf(b[i], b[i], v[3]);
    w[0] += a[i + 1]; w[1] = fmaf(a[i + 1], a[i + 1], w[1]); w[2] += b[i + 1]; w[3] = fmaf(b[i + 1], b[i + 1], w[3]);
  }
#pragma unroll
  for (int e = 0; e < 4; e++) v[e] += w[e];
#pragma unroll
  for (int o = 16; o; o >>= 1) {
#pragma unroll
    for (int e = 0; e < 4; e++) v[e] += __shfl_xor_sync(0xffffffffu, v[e], o);
  }
  const float ma = v[0] * (1.0f / D_), mb = v[2] * (1.0f / D_);
  ra = sc * rsq(fmaxf(fmaf(-ma, ma, v[1] * (1.0f / D_)), 0.f) + 1e-5f);
  rb = sc * rsq(fmaxf(fmaf(-mb, mb, v[3] * (1.0f / D_)), 0.f) + 1e-5f);
  oa = -ma * ra; ob = -mb * rb;
}

__device__ __forceinline__ void ln_stats1(const float (&a)[18], float sc, float& oa, float& ra) {
  float v[3] = {a[0], a[1], a[2]}, w[3] = {a[0] * a[0], a[1] * a[1], a[2] * a[2]};
#pragma unroll
  for (int i = 3; i < 18; i++) { v[i % 3] += a[i]; w[i % 3] = fmaf(a[i], a[i], w[i % 3]); }
  float s = v[0] + v[1] + v[2], q = w[0] + w[1] + w[2];
#pragma unroll
  for (int o = 16; o; o >>= 1) { s += __shfl_xor_sync(0xffffffffu, s, o); q += __shfl_xor_sync(0xffffffffu, q, o); }
  const float m = s * (1.0f / D_);
  ra = sc * rsq(fmaxf(fmaf(-m, m, q * (1.0f / D_)), 0.f) + 1e-5f);
  oa = -m * ra;
}

__device__ __forceinline__ float tmat(int c, int q, int j) {
  const int ph = q == 1 ? 1024 * j : (q >> 1) * (c + 128 * j) + 512 * (q & 1);
  return __cosf((float)(((ph + 1024) & 2047) - 1024) * (6.283185307179586f / 2048.0f));
}
__device__ __forceinline__ uint32_t line_off(int k1, int kap, int pi, int f) {
  int kd = 64 * k1 + 9 * kap;
  if (kap == 0 && k1 > 4) kd -= 288;
  if (kd >= D_) kd -= D_;
  return pi * 2400 + ((min(kd, D_ - kd) ^ f) << 3);
}

struct Ring { uint32_t st, ph; };
template <bool G2, class T> __device__ __forceinline__ void ring_next(T& st, T& ph) {
  if (++st == NST) st = 0;
  ph ^= ((G2 ? 0xDu : 0x1u) >> st) & 1;
}
__device__ __forceinline__ void arrive_if(uint32_t a, uint32_t p) {
  asm volatile("{\n.reg .pred p;\nsetp.ne.u32 p, %1, 0;\n@p mbarrier.arrive.shared::cta.b64 _, [%0];\n}" ::"r"(a), "r"(p) : "memory");
}
template <int NA> __device__ __forceinline__ void reg_fence_n(float (&d)[96]) {
#pragma unroll
  for (int i = 0; i < NA; i++) asm volatile("" : "+f"(d[i])::"memory");
}
template <int MODE>
__device__ __forceinline__ void gemm_main(float (&acc)[96], uint32_t da0, uint32_t da1, uint32_t db0, int wg, Ring& rg,
                                          bool rows, int J, uint32_t* x1p, const uint32_t (&xr)[18]) {
  constexpr int NKB = MODE == 3 ? 36 : 32;
  constexpr uint32_t HA = 0x40000040u, HB = MODE == 3 ? 0xC0000010u : 0x80000020u;
  constexpr uint32_t KA = 2048 >> 4, KB = (MODE == 3 ? 512 : 1024) >> 4;
  constexpr int NA = MODE == 3 ? 72 : MODE == 1 ? 96 : 80;
  const uint32_t t = threadIdx.x & 127;
  const uint32_t eb = full0 + 8 * NST;
  uint32_t pb = 0, rel = t == 0, prel = 0, ok = 0;
  int n = MODE == 3 ? NKB - J : X1K + 2 * wg;
#pragma unroll 1
  for (int pass = MODE == 3 ? 0 : -1;; pass++) {
#pragma unroll 1
    do {
      const uint32_t so = rg.st * ((MODE == 3 ? STAGE2 : STAGE) >> 4), cb = eb + 8 * rg.st;
      if (__builtin_expect(!ok, 0)) mbar_wait(full0 + 8 * rg.st, rg.ph);
      reg_fence_n<NA>(acc);
      if (MODE == 1 && wg) {
        wg_fence();
#pragma unroll
        for (int k = 0; k < 4; k++) wgmma_ss<96, 48, 1>(acc, da1 + so + k * KA, HA, db0 + so + k * KB, HB);
        wg_commit();
      }
      wg_fence();
#pragma unroll
      for (int k = 0; k < 4; k++) {
        if (k == 3) { ring_next<MODE == 3>(rg.st, rg.ph); ok = PEEK ? mbar_test(full0 + 8 * rg.st, rg.ph) : 0; }
        if (MODE == 0) wgmma_ss<160, 0, 1>(acc, da0 + so + k * KA, HA, db0 + so + k * KB, HB);
        else if (MODE == 3) wgmma_ss<144, 0, 1>(acc, da0 + so + k * KA, HA, db0 + so + k * KB, HB);
        else wgmma_ss<96, 0, 1>(acc, da0 + so + k * KA, HA, db0 + so + k * KB, HB);
      }
      wg_commit();
      wg_wait<1>();
      reg_fence_n<NA>(acc);
      arrive_if(pb, prel);
      pb = cb; prel = rel;
    } while (--n);
    if (pass == 2 - wg) break;
    if (MODE != 3 && pass < 0) {
      if (rows) {
#pragma unroll
        for (int i = 0; i < 9; i++) { x1p[32 * i] = xr[i]; x1p[512 * 288 + 32 * i] = xr[9 + i]; }
      }
      n = NKB - J - X1K - 2 * wg;
      continue;
    }
    n = 1;
    if (pass == 0) {
      if (MODE == 0 && J < NST) prel = rel & wg;
      if (MODE == 3) rel = 0;
      n = J - 1 + wg;
      if (!wg) continue;
      wg_wait<0>();
      arrive_if(pb, prel);
      prel = 0;
    }
    bar_sync(1, 256);
  }
  wg_wait<0>();
  reg_fence_n<NA>(acc);
  if (MODE != 3) arrive_if(pb, prel);
}

constexpr float GK1 = 2.0f * 0.7978845608028654f, GK3 = 8.0f * 0.044715f * 0.7978845608028654f;

__device__ __forceinline__ int kb2_order(int i) { const int wv = i / 6; return 6 * (i - 6 * wv) + ((0x431250 >> (4 * wv)) & 7); }

__device__ __forceinline__ int kb2_pos(int kb) { const int hf = kb >= 36, k = kb - 36 * hf, gr = k / 6; return 64 * hf + gr + 6 * ((0x154230 >> (4 * (k - 6 * gr))) & 7); }

__device__ __forceinline__ void wait_flags(const unsigned* p, int idx, unsigned target, uint32_t& ready) {
  int it = 0;
  while (!((ready >> idx) & 1) && it++ < SPIN_MAX) ready = __ballot_sync(0xffffffffu, (int)(ld_rlx(p) - target) >= 0);
}

enum { B_FULL = 0, B_EMPTY = 6, B_S4 = 12, B_S5, B_LAND, B_FLT = B_LAND + 6, B_Z1, B_Z2, B_GO, B_X, B_WM, B_NUM, B_W0 = B_NUM };

__global__ void __launch_bounds__(NTHR, 1)
fused_kernel(const Params p, const __grid_constant__ Maps maps) {
  extern __shared__ __align__(1024) uint8_t smem_raw[];
  const int bx = blockIdx.x, cta = bx < 112 || bx >= 130 ? bx : bx < 114 ? bx + 16 : bx - 2;
  const int tid = threadIdx.x, t128 = tid & 127;
  const int wp = __shfl_sync(0xffffffffu, tid >> 5, 0), wg = wp >> 2;
  const int l = tid & 31, g = l >> 2, t = l & 3;
  Scratch* const sc = p.s;
  const bool rows = cta < 128;
  const int mu = rows ? cta + 4 : cta - 128;
  const int R = mu - 12;

  uint32_t xr[18];
  uint32_t cv[3];
  const unsigned ep0 = ld_rlx(&sc->cnt[C_EP + l]);
  if (tid == 0) TS(0);
  if (wg == 2) {
#pragma unroll
    for (int i = 0; i < 3; i++) cv[i] = ld_nc(reinterpret_cast<const uint32_t*>(p.c) + min(t128 + 128 * i, 287));
    if (wp == 9 && l < 9 && rows) {
      const int h = 9 * cta + l;
      prefetch_l2(reinterpret_cast<const uint8_t*>(p.wmod) + (size_t)(h >> 1) * (12 * D_) + (h & 1) * (2 * D_), 2 * D_);
    }
    if (tid == 256 && mu < 72) {
      mbar_init(full0 + 8 * B_W0, 1);
      fence_async_smem();
      mbar_expect(full0 + 8 * B_W0, 18432);
#pragma unroll 1
      for (int i = 0; i < 3; i++) tma2d(sbase + O_P2 + i * 6144, &maps.wm, 16 * mu, 192 * i, full0 + 8 * B_W0);
    }
    __syncwarp();
#pragma unroll 1
    for (int u = mu < 72 ? mu : 72 + mu; u < 216; u += u < 72 ? 72 : NCTA) if (u < 72 || t128 < 16) *mod_ptr(sc, u, t128) = 0;
    if (wp == 11 && smem_u32(smem_raw) != sbase) __trap();
    if (wp >= 10 && elect()) {
#pragma unroll 1
      for (int i = wp - 10; i < B_NUM; i += 2) mbar_init(full0 + 8 * i, i == B_FLT ? 4 : i == B_WM ? 3 : i < B_S4 ? 2 : 1);
      fence_async_smem();
    }
    __syncwarp();
  } else if (rows) {
    const uint32_t* xs = reinterpret_cast<const uint32_t*>(p.x) + (size_t)(cta + 128 * ((wp & 3) + 8 * wg)) * 288 + l;
#pragma unroll
    for (int i = 0; i < 9; i++) { xr[i] = ld_nc(xs + 32 * i); xr[9 + i] = ld_nc(xs + 512 * 288 + 32 * i); }
  }
  CK(0);
  if (tid == 64 && cta == NCTA - 1) prefetch_l2(p.tab, sizeof(T_TAB));
  __syncwarp();
  auto tag_of = [](unsigned e) { return (e & 0x7fffu) | 0x8000u; };
  const int kap = 8 * ((wp & 3) ^ (wg & 1)) + g;
  uint32_t tb[4], sb1[3], lo[9];
#pragma unroll
  for (int i = 0; i < 4; i++) tb[i] = pin(pack_bf16(tmat(cta, 8 * (i >> 1) + g, t + 8 * (i & 1)), tmat(cta, 8 * (i >> 1) + g, t + 8 * (i & 1) + 4)));
#pragma unroll
  for (int i = 0; i < 3; i++) {
    const int d = 48 * wp + 16 * i + (l & 15);
    sb1[i] = pin(sbase + O_B1 + (l >> 4) * 9216 + (d % 9) * 1024 + (d & 63) * 16);
  }
#pragma unroll
  for (int k1 = 0; k1 < 9; k1++) lo[k1] = pin(sbase + O_Z1 + line_off(k1, kap, 4 * wg + t, cta & 3));
  const uint32_t snt = pin(sbase + O_NRM + ((l & 7) + 8 * (l >> 4)) * 1168 + (48 * wp + (l & 8)) * 2), sn = pin(sbase + O_NRM + wp * 2336 + l * 4);
  const uint32_t smask = pin(t ? 0u : 0xffff0000u);
  const uint32_t* const mp = pin(sc->moda + (cta >> 4) * (2 * D_) + 48 * wp + 2 * g);
  const uint4* const ftab = pin(p.tab + TB_F + (t128 ^ (wg << 5)));

  if (wg == 2) {
#pragma unroll
    for (int i = 0; i < 3; i++) {
      const float c0 = bf_lo(cv[i]), c1 = bf_hi(cv[i]);
      sts(red + 512 + min(t128 + 128 * i, 287) * 4, pack_bf16(__fdividef(c0, 1.0f + __expf(-c0)), __fdividef(c1, 1.0f + __expf(-c1))));
    }
    if (t128 == 0) sts(full0 + 248, ep0 + 1);
    if (wp == 9 && l < 11) asm volatile("prefetch.tensormap [%0];" ::"l"(&maps.z1 + l) : "memory");
    bar_sync(4, 128);
    if (mu < 72) {
      mod_unit(sc, mu, t128, sbase + O_P2, full0 + 8 * B_W0, 0, red, tag_of(upin(ep0) + 1));
      if (t128 == 0) TS(25);
    }
    CK(1);
  }
  const int pi = R / 15, col0 = 20 * (R - 15 * pi);
  const int xu = DF_ * pi + col0, xv = DF_ * (pi ? 16 - pi : 8) + col0;
  auto load_filter = [&](int a) {
    const int x = (a & 1) ? xv : xu;
    const bool wide = (x & 15) > 12;
    mbar_expect(full0 + 8 * B_FLT, wide ? 12288 : 8192);
    tma2d(sbase + O_RAW + a * 12288, &maps.wf[a & 2], x & ~15, 0, full0 + 8 * B_FLT);
    if (wide) tma2d(sbase + O_RAW + a * 12288 + 8192, &maps.wf[(a & 2) + 1], (x & ~15) + 32, 0, full0 + 8 * B_FLT);
  };
  uint4 af[4];
  if (rows) {
    uint2 ms[3], mc[3];
    auto load_mod = [&](uint32_t o = 0) {
#pragma unroll
      for (int i = 0; i < 3; i++) { ms[i] = ld_rlx2(mp + 2 * o + 16 * i); mc[i] = ld_rlx2(mp + 2 * o + D_ + 16 * i); }
    };
    if (wg < 2) {
      float a[18], b[18];
#pragma unroll
      for (int i = 0; i < 9; i++) { a[2 * i] = bf_lo(xr[i]); a[2 * i + 1] = bf_hi(xr[i]); b[2 * i] = bf_lo(xr[9 + i]); b[2 * i + 1] = bf_hi(xr[9 + i]); }
      float oa, ra, ob, rb;
      ln_stats2(a, b, 1.0f, oa, ra, ob, rb);
      CK(1);
      load_mod((__float_as_uint(ra) | __float_as_uint(rb)) >> 31);
#pragma unroll
      for (int i = 0; i < 9; i++) {
        sts(sn + i * 128, pack_bf16(fmaf(a[2 * i], ra, oa), fmaf(a[2 * i + 1], ra, oa)));
        sts(sn + 1168 + i * 128, pack_bf16(fmaf(b[2 * i], rb, ob), fmaf(b[2 * i + 1], rb, ob)));
      }
      CK(2);
      bar_arrive(10, NTHR);
#pragma unroll
      for (int kk = 0; kk < 4; kk++) af[kk] = ld_nc4(ftab + kk * 128);
      bar_sync(1, 256);
      if (tid == 0) TS(2);
    } else {
      bar_sync(10, NTHR);
      load_mod();
      CK(2);
      if (wp >= 10 && elect()) prefetch_l2(reinterpret_cast<const uint8_t*>(wp == 10 ? p.wr : p.wi) + cta * 9248, 9248);
      __syncwarp();
    }
    float rs[3][8];
#pragma unroll
    for (int i = 0; i < 3; i++) {
      uint32_t a0, a1, a2, a3;
      asm volatile("ldmatrix.sync.aligned.m8n8.x4.trans.shared.b16 {%0,%1,%2,%3}, [%4];" : "=r"(a0), "=r"(a1), "=r"(a2), "=r"(a3)
                   : "r"(snt + 32 * i) : "memory");
      mma16<false>(&rs[i][0], a0, a1, a2, a3, tb[0], tb[1]);
      mma16<false>(&rs[i][4], a0, a1, a2, a3, tb[2], tb[3]);
    }
    CK(3);
    const uint32_t tag16 = tag_of(upin(ep0) + 1), tag1 = tag16 & 1;
    {
      int it = 0;
#pragma unroll 1
      while (true) {
        uint32_t bad = 0;
#pragma unroll
        for (int i = 0; i < 3; i++) bad |= diff2(ms[i].x, ms[i].y, tag16) | diff2(mc[i].x, mc[i].y, tag16);
        if (!any(bad & 0xffffu) || ++it > SPIN_MAX) break;
        load_mod();
      }
      CK(4);
      if (tid == 0) TS(3);
#pragma unroll
      for (int i = 0; i < 3; i++) {
        const float c0 = bf_hi(mc[i].x), c1 = bf_hi(mc[i].y);
        const float s0 = __uint_as_float(ms[i].x & smask), s1 = __uint_as_float(ms[i].y & smask);
        stmatrix4(sb1[i], pack_bf16(fmaf(rs[i][0], c0, s0), rs[i][1] * c0), pack_bf16(fmaf(rs[i][2], c1, s1), rs[i][3] * c1),
                  pack_bf16(rs[i][4] * c0, rs[i][5] * c0), pack_bf16(rs[i][6] * c1, rs[i][7] * c1));
      }
    }
    fence_async_smem();
    CK(5);
    if (wg == 2) {
      bar_arrive(5, NTHR);
      if (R >= 0 && elect()) load_filter(wp - 8);
      __syncwarp();
      const int slot = 4 * (cta & 7) + ((cta >> 4) & 3) + 32 * (2 * (cta >> 6) + ((cta >> 3) & 1));
      const uint32_t c0 = upin(40 * slot), c1 = upin(60 * (wp & 1)), src = upin(sbase + O_Z1 + (wp & 1) * 9600);
      const CUtensorMap* mz = upin(&maps.z1);
      unsigned* hint = pin(sc->cnt + C_Z1 + 32 * (wp & 1));
      if (wp < 10) {
        bar_sync(2 + (wp & 1), 160);
        if (elect()) tma_st2d(mz, src, c0, c1);
        pause(HD1);
        if (elect()) red_add(hint, 1);
        bulk_commit_wait();
        if (tid == 256) TS(4);
        __syncwarp();
      }
    } else {
      bar_sync(5, NTHR);
      CK(6);
      float acc[36];
      const uint32_t db = (((sbase + O_B1 + wg * 9216) & 0x3FFFF) >> 4) | ((128 >> 4) << 16);
      wg_fence();
#pragma unroll
      for (int kk = 0; kk < 4; kk++) wgmma_rs_72(acc, af[kk].x, af[kk].y, af[kk].z, af[kk].w, db + kk * 16, 1024 >> 4, kk);
      wg_commit();
      wg_wait<0>();
      reg_fence(acc);
      CK(7);
      float2 za[9], zb[9];
#pragma unroll
      for (int i = 0; i < 9; i++) { za[i] = make_float2(acc[4 * i], acc[4 * i + 2]); zb[i] = make_float2(acc[4 * i + 1], acc[4 * i + 3]); }
      dft9(za); dft9(zb);
      if ((wp & 3) == wg) {
        const float sp = g ? 0.f : 1.f;
#pragma unroll
        for (int k = 1; k < 5; k++) {
          float2 a = za[k], b = za[9 - k];
          za[k] = make_float2(fmaf(sp, b.x, a.x), fmaf(-sp, b.y, a.y)); za[9 - k] = make_float2(fmaf(-sp, a.x, b.x), fmaf(sp, a.y, b.y));
          a = zb[k]; b = zb[9 - k];
          zb[k] = make_float2(fmaf(sp, b.x, a.x), fmaf(-sp, b.y, a.y)); zb[9 - k] = make_float2(fmaf(-sp, a.x, b.x), fmaf(sp, a.y, b.y));
        }
        const uint32_t w0 = set_tag(pack_bf16(za[0].y, 0.f), tag1), w1 = pack_bf16(zb[0].y, 0.f);
        asm volatile("{\n.reg .pred p;\nsetp.eq.u32 p, %3, 0;\n@p st.shared.v2.b32 [%0], {%1,%2};\n}" ::"r"(lo[0] + 288 * 8), "r"(w0), "r"(w1), "r"(g) : "memory");
        za[0].y = g ? za[0].y : 0.f; zb[0].y = g ? zb[0].y : 0.f;
      }
#pragma unroll
      for (int k1 = 0; k1 < 9; k1++) sts2(lo[k1], set_tag(pack_bf16(za[k1].x, za[k1].y), tag1), pack_bf16(zb[k1].x, zb[k1].y));
      fence_async_smem();
      CK(8);
      bar_arrive(2 + wg, 160);
      {
        const uint32_t fx = (((cta >> 4) ^ cta) & 3) << 3, dl = O_IN - O_Z1, st = sbase + O_ST + 15360 + tid * 16;
        sts4(st, (lo[0] ^ fx) + dl, (lo[1] ^ fx) + dl, (lo[2] ^ fx) + dl, (lo[3] ^ fx) + dl);
        sts4(st + 4096, (lo[4] ^ fx) + dl, (lo[5] ^ fx) + dl, (lo[6] ^ fx) + dl, (lo[7] ^ fx) + dl);
        sts4(st + 8192, (lo[8] ^ fx) + dl, (lo[0] ^ fx) + dl + (kap ? 0 : 288 * 8),
             sbase + O_B3 + wg * 1024 + (l >> 4) * 2048 + (2 * (kap & 24) + (l & 15)) * 16, 0);
      }
    }
    {
      uint32_t sy[6];
#pragma unroll
      for (int i = 0; i < 6; i++) {
        const int rr = 16 * (wp & 3) + g + 8 * (i & 1);
        sy[i] = sbase + O_Y + (t * 584 + 64 * ((3 * wg + (i >> 1) + 63 - rr) % 9) + rr) * 4;
      }
      sts4(sbase + O_ST + tid * 16, movm(tb[0]), movm(tb[2]), movm(tb[1]), movm(tb[3]));
      sts4(sbase + O_ST + 6144 + tid * 16, sy[0], sy[1], sy[2], sy[3]);
      sts2(sbase + O_ST + 12288 + tid * 8, sy[4], sy[5]);
    }
  } else {
    __syncthreads();
  }

  const unsigned ep = upin(lds(full0 + 248));
  const uint32_t tag16 = tag_of(ep), tag1 = ep & 1;
  auto load_wm = [&](int u) {
    if (wp > 8 && elect()) {
      mbar_expect(full0 + 8 * B_WM, 6144);
      tma2d(sbase + O_NRM + (wp - 9) * 6144, &maps.wm, 16 * u, 192 * (wp - 9), full0 + 8 * B_WM);
    }
    __syncwarp();
  };
  if (R >= 0) {
    const int nl = (col0 + wp < DF_) + (wg < 2 && col0 + wp + 12 < DF_);
    uint4 cf[2][4], G[4];
#pragma unroll
    for (int i = 0; i < 4; i++) {
      cf[0][i] = __ldg(p.tab + TB_P2 + i * 32 + l);
      cf[1][i] = __ldg(p.tab + TB_P2 + (pi ? i : 4 + i) * 32 + l);
      G[i] = __ldg(p.tab + TB_P2 + (8 + i) * 32 + l);
    }
    const uint32_t* zin = sc->z1 + (size_t)R * 5120;
    if (wp == 10) {
      const uint32_t* zu = upin(zin);
      if (elect()) mbar_expect(full0 + 8 * B_Z1, 20480);
      wait_cnt(sc->cnt + C_Z1 + 32 * (pi >> 2), 128 * ep - 40 * STRESS);
      if (elect()) {
        bulk_ld(sbase + O_P2, zu, 20480, full0 + 8 * B_Z1);
        TS(12);
      }
      __syncwarp();
    }
    mbar_wait(full0 + 8 * B_FLT, 0);
    CK(9);
    float wn[16], wc[16];
#pragma unroll 1
    for (int ln = nl - 1; ln >= 0; ln--) {
      const int col = col0 + wp + 12 * ln, k2 = (57 * col) & 63;
      const bool cj = k2 > 32;
      const float nr = ((col & 31) == 0 && col != 0 && col != 288 ? 0.5f : 1.0f) / ((float)S_ * D_), ni = cj ? -nr : nr;
#pragma unroll
      for (int i = 0; i < 16; i++) wn[i] = wc[i];
#pragma unroll
      for (int cl = 0; cl < 2; cl++) {
        const int v = cl ^ (cj && pi), e = ((v ? xv : xu) & 15) + wp + 12 * ln, sh = e < 32 ? 6 : 5;
        const uint32_t base = sbase + O_RAW + v * 12288 + (e < 32 ? 2 * e : 8192 - 64 + 2 * e), msk = e < 32 ? 0x30 : 0x10;
        const int dm = v ? (cj || pi ? -1 : 0) : 0;
#pragma unroll
        for (int tt = 0; tt < 4; tt++) {
          const int kc = g + 64 * (tt >> 1) + 16 * t + 8 * (tt & 1);
          uint32_t a = base + ((((cj ? -kc : kc) + dm) & 127) << sh);
          a ^= (a >> 3) & msk;
          wc[4 * tt + 2 * cl] = lds_bf(a) * nr; wc[4 * tt + 2 * cl + 1] = lds_bf(a + 24576) * ni;
        }
      }
    }
    const float al = __uint_as_float(pin((pi ? 0x3f800000u : 0u) + (l >> 5)));
    const uint32_t tagv = pin(tag1 + (l >> 5));
    CK(10);
    uint32_t off = pin(l * 160 + ((wp ^ (g & 3)) << 3));
    uint32_t offo = pin(sbase + O_P2 + 20480 + off - 64 * l), po = 3072;
    unsigned* hz2 = pin(sc->cnt + C_Z2);
    const uint32_t do2 = pin(12288 - 32 * l);
    const CUtensorMap* mz2 = upin(&maps.z2[wp == 0]);
    const uint32_t sz2 = upin(sbase + O_P2 + 20480 + (wp ? 0 : 12288)), cz2 = upin(40 * R + (wp ? 0 : 24));
    mbar_wait(full0 + 8 * B_Z1, 0);
    CK(11);
    if (tid == 0) TS(8);
    if (wg == 2) load_wm(72 + mu);
    uint2 v[4], v2[4];
    const uint32_t o2 = nl > 1 ? 96 : 0;
#pragma unroll
    for (int i = 0; i < 4; i++) { v[i] = lds2(sbase + O_P2 + off + i * 5120); v2[i] = lds2(sbase + O_P2 + off + o2 + i * 5120); }
    auto bad2 = [&]() {
      return any(or3(or3(diff2(v[0].x, v[1].x, tagv), diff2(v[2].x, v[3].x, tagv), diff2(v2[0].x, v2[1].x, tagv)), diff2(v2[2].x, v2[3].x, tagv), 0) & 1);
    };
    if (__builtin_expect(bad2() && nl, 0)) {
      FAILCNT(0);
      int it = 0;
      do {
#pragma unroll
        for (int i = 0; i < 4; i++) {
          v[i] = ld_rlx2(reinterpret_cast<const uint8_t*>(zin) + off + i * 5120);
          v2[i] = ld_rlx2(reinterpret_cast<const uint8_t*>(zin) + off + o2 + i * 5120);
        }
      } while (bad2() && ++it < SPIN_MAX);
    }
#pragma unroll 1
    for (int ln = 0; ln < nl; ln++, offo += do2, po = 2048) {
      float d[4][4];
      uint32_t A[8];
#pragma unroll
      for (int h = 0; h < 2; h++) {
        mma16<false>(d[2 * h], cf[0][0].x, cf[0][0].y, cf[0][0].z, cf[0][0].w, v[h].x, v[2 + h].x);
        mma16<false>(d[2 * h + 1], cf[1][0].x, cf[1][0].y, cf[1][0].z, cf[1][0].w, v[h].y, v[2 + h].y);
      }
      if (ln) { fence_async_smem(); bar_arrive(15, NTHR); }
#pragma unroll
      for (int h = 0; h < 2; h++)
#pragma unroll
        for (int L = 0; L < 2; L++) {
          const uint4 tw = cf[L][2 + h];
          const float* z = d[2 * h + L];
          const float2 z0 = cmul(make_float2(z[0], z[2]), make_float2(__uint_as_float(tw.x), __uint_as_float(tw.y)));
          const float2 z1 = cmul(make_float2(z[1], z[3]), make_float2(__uint_as_float(tw.z), __uint_as_float(tw.w)));
          A[4 * h + L] = pack_bf16(z0.x, z0.y); A[4 * h + 2 + L] = pack_bf16(z1.x, z1.y);
        }
#pragma unroll
      for (int tt = 0; tt < 4; tt++) {
        mma16<false>(d[tt], A[0], A[1], A[2], A[3], G[tt].x, G[tt].y);
        mma16<true>(d[tt], A[4], A[5], A[6], A[7], G[tt].z, G[tt].w);
      }
#pragma unroll
      for (int tt = 0; tt < 4; tt++) {
        const float ar = d[tt][0], aj = d[tt][1], br = d[tt][2], bj = d[tt][3];
        const float2 y1 = cmul(make_float2(fmaf(-al, bj, ar), fmaf(al, br, aj)), make_float2(wc[4 * tt], wc[4 * tt + 1]));
        const float2 y2 = cmul(make_float2(fmaf(al, ar, bj), fmaf(al, aj, -br)), make_float2(wc[4 * tt + 2], wc[4 * tt + 3]));
        A[2 * tt] = pack_bf16(fmaf(al, y2.x, y1.x), fmaf(-al, y2.y, -y1.y));
        A[2 * tt + 1] = pack_bf16(fmaf(al, y1.y, -y2.y), fmaf(al, y1.x, -y2.x));
      }
#pragma unroll
      for (int i = 0; i < 16; i++) wc[i] = wn[i];
#pragma unroll
      for (int i = 0; i < 4; i++) v[i] = v2[i];
#pragma unroll
      for (int tt = 0; tt < 4; tt++) {
        mma16<false>(d[tt], A[0], A[1], A[2], A[3], G[tt].x, G[tt].y);
        mma16<true>(d[tt], A[4], A[5], A[6], A[7], G[tt].z, G[tt].w);
      }
#pragma unroll
      for (int h = 0; h < 2; h++)
#pragma unroll
        for (int L = 0; L < 2; L++) {
          const uint4 tw = cf[L][2 + h];
          const float2 z0 = cmul(make_float2(d[2 * h][2 * L], d[2 * h][2 * L + 1]), make_float2(__uint_as_float(tw.x), __uint_as_float(tw.y)));
          const float2 z1 = cmul(make_float2(d[2 * h + 1][2 * L], d[2 * h + 1][2 * L + 1]), make_float2(__uint_as_float(tw.z), __uint_as_float(tw.w)));
          A[4 * h + 2 * L] = movm(pack_bf16(z0.x, z1.x)); A[4 * h + 2 * L + 1] = movm(pack_bf16(z0.y, z1.y));
        }
#pragma unroll
      for (int h = 0; h < 2; h++) {
        mma16<false>(d[0], cf[0][1].x, cf[0][1].y, cf[0][1].z, cf[0][1].w, A[4 * h], A[4 * h + 1]);
        mma16<false>(d[1], cf[1][1].x, cf[1][1].y, cf[1][1].z, cf[1][1].w, A[4 * h + 2], A[4 * h + 3]);
#pragma unroll
        for (int e = 0; e < 2; e++)
          sts2(offo + (2 * h + e) * po, set_tag(pack_bf16(d[0][e], d[0][2 + e]), tagv), pack_bf16(d[1][e], d[1][2 + e]));
      }
      CK(12 + ln);
    }
    if (tid == 0) TS(1);
    fence_async_smem();
    if (nl < 2 && wp != 8) bar_arrive(15, NTHR);
    if (wp) bar_arrive(6, NTHR);
    if (!(wp & 7)) {
      bar_sync(wp ? 15 : 6, NTHR);
      if (elect()) tma_st2d(mz2, sz2, cz2, 0);
      if (wp == 0 && elect()) red_add(hz2, 1);
      if (tid == 0) TS(9);
      if (wp == 0) bulk_commit_wait();
      __syncwarp();
    }
  }
  if (wg == 2) {
#pragma unroll 1
    for (int u = 72 + mu, k = 0; u < 216; u += NCTA, k ^= 1) {
      if (R < 0) { fence_async_smem(); bar_sync(4, 128); load_wm(u); }
      mod_unit(sc, u, t128, sbase + O_NRM, full0 + 8 * B_WM, k, red + 256 - 256 * k, tag16);
    }
    fence_async_smem();
    CK(13);
  }

  const int grp = bx / 11, m1 = bx - 11 * grp;
  const bool helper = (m1 & 3) == 3;
  const int f1 = 384 * grp + (helper ? 192 : 128) * (m1 >> 2);
  const int d1 = 160 * (m1 & 3), flip = m1 >= 7;
  const int a1bytes = helper ? 24576 : 16384;
  auto load_a1 = [&](int st, int kb) {
    mbar_expect(full0 + 8 * st, a1bytes);
    tma4d_ef(sbase + st * STAGE, helper ? &maps.w1b : &maps.w1a, 4 * (kb >> 3), 16 * (kb & 7), f1 >> 6, full0 + 8 * st);
  };

  uint32_t bia[4];
  if (wg < 2) {
    const int fa = f1 + (helper ? 128 : 64) * (wg ^ flip) + 16 * (wp & 3) + g, fb = helper ? f1 + 64 + 16 * (wp & 3) + g : fa;
#pragma unroll
    for (int i = 0; i < 4; i++) asm volatile("ld.global.nc.u16 %0, [%1];" : "=r"(bia[i]) : "l"(p.b1 + (i < 2 ? fa : fb) + 8 * (i & 1)) : "memory");
  }
  if (rows) {
#pragma unroll
    for (int kk = 0; kk < 4; kk++) af[kk] = __ldg(p.tab + TB_E + kk * 128 + t128);
    const uint4 c0 = lds4(sbase + O_ST + tid * 16), c1 = lds4(sbase + O_ST + 6144 + tid * 16);
    const uint2 c2 = lds2(sbase + O_ST + 12288 + tid * 8);
    const uint32_t tc[4] = {c0.x, c0.y, c0.z, c0.w}, sy[6] = {c1.x, c1.y, c1.z, c1.w, c2.x, c2.y};
    const uint32_t l8 = pin(8 * l), syl = pin(sbase + O_Y + wp * 2336 + 8 * l);
    uint32_t sh3[3], ham[3];
#pragma unroll
    for (int k = 0; k < 3; k++) {
      const int pos = k && (l >> 4) == k - 1 ? 2 * (l & 6) + ((l >> 2) & 2) + (l & 1) : l & 15;
      const int sw = 2 * cta + ((wp >> 1) & 1), ph = pos ^ ((sw & 3) << 2);
      sh3[k] = pin((l >> 4) * 256 + (wp & 3) * 64 + ph * 4);
      ham[k] = pin(((ph ^ sw) & 7) == 0 ? ~1u : ~0u);
    }
    unsigned* const hh3 = upin(sc->cnt + C_H3 + (cta >> 4));
    uint8_t* const h3g = pin(sc->h3 + (cta >> 4) * (18 * 4096) + (cta & 15) * 256 + (l >> 4) * 3840);
    const int slot = 4 * (cta >> 4) + ((cta >> 1) & 3) + 32 * (2 * ((cta >> 3) & 1) + (cta & 1));
    const uint32_t* zin = sc->z2 + (size_t)slot * 4800;
    if (wg == 2) {
      {
        uint4 v[4];
        const int i3 = min(t128 + 384, 431);
        int it = 0;
        while (true) {
          uint32_t bad = 0;
#pragma unroll
          for (int k = 0; k < 4; k++) v[k] = ld_rlx4(sc->mod + 4 * (k < 3 ? t128 + 128 * k : i3));
#pragma unroll
          for (int k = 0; k < 4; k++) {
            v[k].x ^= tag16; v[k].y ^= tag16; v[k].z ^= tag16; v[k].w ^= tag16;
            bad |= v[k].x | v[k].y | v[k].z | v[k].w;
          }
          if (!any(bad & 0xffffu) || ++it > SPIN_MAX) break;
        }
#pragma unroll
        for (int k = 0; k < 4; k++) sts4(sbase + O_MOD + 16 * (k < 3 ? t128 + 128 * k : i3), v[k].x, v[k].y, v[k].z, v[k].w);
      }
      CK(14);
      bulk_commit_wait();
      bar_sync(10, NTHR);
      mbar_wait(full0 + 8 * B_Z2, 0);
      if (elect()) {
        load_a1(wp - 8, wp - 8);
      }
      __syncwarp();
    } else {
      const uint4 e0 = lds4(sbase + O_ST + 15360 + tid * 16), e1 = lds4(sbase + O_ST + 19456 + tid * 16), e2 = lds4(sbase + O_ST + 23552 + tid * 16);
      const uint32_t li[9] = {e0.x, e0.y, e0.z, e0.w, e1.x, e1.y, e1.z, e1.w, e2.x}, lx = e2.y, sb3 = e2.z;
      bar_arrive(10, NTHR);
      CK(14);
      if (wp == 1) {
        const uint32_t* zu = upin(zin);
        if (elect()) mbar_expect(full0 + 8 * B_Z2, 19200);
        wait_cnt(sc->cnt + C_Z2, 120 * ep - 40 * STRESS);
        if (elect()) {
          bulk_ld(sbase + O_IN, zu, 19200, full0 + 8 * B_Z2);
          TS(14);
        }
        __syncwarp();
      }
      mbar_wait(full0 + 8 * B_Z2, 0);
      CK(15);
      if (tid == 0) TS(11);
      uint2 v[10];
#pragma unroll
      for (int k1 = 0; k1 < 10; k1++) v[k1] = lds2(k1 < 9 ? li[k1] : lx);
      auto bad3 = [&]() {
        return any(or3(or3(diff2(v[0].x, v[1].x, tag1), diff2(v[2].x, v[3].x, tag1), diff2(v[4].x, v[5].x, tag1)), diff2(v[6].x, v[7].x, tag1), diff2(v[8].x, v[9].x, tag1)) & 1);
      };
      if (__builtin_expect(bad3(), 0)) {
        FAILCNT(1);
        int it = 0;
        do {
#pragma unroll
          for (int k1 = 0; k1 < 10; k1++) v[k1] = ld_rlx2(reinterpret_cast<const uint8_t*>(zin) + ((k1 < 9 ? li[k1] : lx) - (sbase + O_IN)));
        } while (bad3() && ++it < SPIN_MAX);
      }
      float2 za[9], zb[9];
#pragma unroll
      for (int i = 0; i < 9; i++) { za[i] = make_float2(bf_lo(v[i].x), bf_hi(v[i].x)); zb[i] = make_float2(bf_lo(v[i].y), bf_hi(v[i].y)); }
      if ((wp & 3) == wg) {
        const float sp = g ? 0.f : 1.f;
#pragma unroll
        for (int k = 1; k < 5; k++) {
          float2 a = za[k], b = za[9 - k];
          za[k] = make_float2(fmaf(-sp, b.x, a.x), fmaf(sp, b.y, a.y)); za[9 - k] = make_float2(fmaf(sp, a.x, b.x), fmaf(-sp, a.y, b.y));
          a = zb[k]; b = zb[9 - k];
          zb[k] = make_float2(fmaf(-sp, b.x, a.x), fmaf(sp, b.y, a.y)); zb[9 - k] = make_float2(fmaf(sp, a.x, b.x), fmaf(-sp, a.y, b.y));
        }
        za[0].y = g ? za[0].y : bf_lo(v[9].x); zb[0].y = g ? zb[0].y : bf_lo(v[9].y);
      }
      dft9(za); dft9(zb);
#pragma unroll
      for (int n = 0; n < 8; n += 2) {
        const int i0 = (9 - n) % 9, i1 = 8 - n;
        stmatrix4(sb3 + n * 2048, pack_bf16(za[i0].x, zb[i0].x), pack_bf16(za[i0].y, zb[i0].y), pack_bf16(za[i1].x, zb[i1].x), pack_bf16(za[i1].y, zb[i1].y));
      }
      stmatrix2(sb3 + 8 * 2048, pack_bf16(za[1].x, zb[1].x), pack_bf16(za[1].y, zb[1].y));
      fence_async_smem();
    }
    CK(16);
    __syncthreads();
    CK(17);
    float acc[24];
    const uint32_t db = (((sbase + O_B3 + wg * 6144) & 0x3FFFF) >> 4) | ((128 >> 4) << 16);
    wg_fence();
#pragma unroll
    for (int kk = 0; kk < 4; kk++) wgmma_rs_48(acc, af[kk].x, af[kk].y, af[kk].z, af[kk].w, db + kk * 16, 1024 >> 4, kk);
    wg_commit();
    uint32_t ga[9];
    if (wg < 2) {
#pragma unroll
      for (int i = 0; i < 9; i++) { const uint2 v = lds2(l8 + sbase + O_MOD + 256 * i); ga[i] = __byte_perm(v.x, v.y, 0x7632); }
    }
    wg_wait<0>();
    reg_fence(acc);
    CK(18);
#pragma unroll
    for (int i = 0; i < 3; i++) {
      const float* a = &acc[8 * i];
      const uint32_t a0 = pack_bf16(a[0], a[1]), a1 = pack_bf16(a[2], a[3]), a2 = pack_bf16(a[4], a[5]), a3 = pack_bf16(a[6], a[7]);
#pragma unroll
      for (int jh = 0; jh < 2; jh++) {
        float y[4];
        mma16<false>(y, a0, a1, a2, a3, tc[2 * jh], tc[2 * jh + 1]);
        sts(sy[2 * i] + jh * (4 * 584 * 4), pack_bf16(y[0], y[1]));
        sts(sy[2 * i + 1] + jh * (4 * 584 * 4), pack_bf16(y[2], y[3]));
      }
    }
    CK(19);
    if (wg == 2) bar_arrive(7, NTHR); else bar_sync(7, NTHR);
    if (wg) bar_sync(15, NTHR);
    if (wg < 2) {
      CK(20);
      uint2 y[9], sh[9], sw[9];
#pragma unroll
      for (int i = 0; i < 9; i++) y[i] = lds2(syl + 256 * i);
      uint32_t sel = 0x5410, sto = sbase + O_B3 + wg * 9216;
#pragma unroll 1
      for (int e = 0; e < 2; e++, sel = 0x7632, sto += 4608) {
        float a[18];
#pragma unroll
        for (int i = 0; i < 9; i++) {
          const uint32_t x1 = hfma2(ga[i], __byte_perm(y[i].x, y[i].y, sel), xr[i]);
          xr[i] = xr[9 + i]; xr[9 + i] = x1;
          a[2 * i] = bf_lo(x1); a[2 * i + 1] = bf_hi(x1);
        }
#pragma unroll
        for (int i = 0; i < 9; i++) { lds2_if(!e, sh[i], l8 + sbase + O_MOD + 4 * D_ + 256 * i); lds2_if(!e, sw[i], l8 + sbase + O_MOD + 8 * D_ + 256 * i); }
        float oa, ra;
        ln_stats1(a, 1.0f, oa, ra);
#pragma unroll
        for (int i = 0; i < 9; i++) {
          a[2 * i] = fmaf(fmaf(a[2 * i], ra, oa), __uint_as_float(sw[i].x), __uint_as_float(sh[i].x));
          a[2 * i + 1] = fmaf(fmaf(a[2 * i + 1], ra, oa), __uint_as_float(sw[i].y), __uint_as_float(sh[i].y));
        }
        ln_stats1(a, 0.5f, oa, ra);
        uint32_t hv[9];
#pragma unroll
        for (int i = 0; i < 9; i++) hv[i] = bitsel(pack_bf16(fmaf(a[2 * i], ra, oa), fmaf(a[2 * i + 1], ra, oa)), ham[i == 2 ? 1 : i == 6 ? 2 : 0], tag1);
        if (!(wg | e)) {
          if (elect()) red_add(hh3, 1);
#pragma unroll
          for (int i = 0; i < 9; i++) asm volatile("st.global.b32 [%0], %1;" ::"l"(h3g + sh3[i == 2 ? 1 : i == 6 ? 2 : 0] + i * 8192), "r"(hv[i]) : "memory");
          bar_arrive(15, NTHR);
          if (tid == 0) TS(13);
        } else {
#pragma unroll
          for (int i = 0; i < 9; i++) sts(sto + sh3[i == 2 ? 1 : i == 6 ? 2 : 0] + i * 512, hv[i]);
        }
        if (!e) bar_arrive(8, 288);
        CK(21 + e);
      }
      fence_async_smem();
      bar_arrive(9, 288);
      CK(23);
    }
  }

  const bool g2 = rows;
  const int z2 = cta, r = z2 >> 6;
  const int s2 = 128 * ((z2 >> 2) & 15), d2 = 144 * (z2 & 3);
  constexpr int ST0 = 32 % NST;
  const bool first = helper || m1 < W0N;

  if (wg == 2) {
    asm volatile("setmaxnreg.dec.sync.aligned.u32 40;");
    auto load_b = [&](bool second, int i, int st) {
      const uint32_t lb = full0 + 8 * (B_LAND + st), bytes = second ? 18432 : STAGE - a1bytes;
      mbar_expect(lb, bytes);
      bulk_ld(sbase + (second ? st * STAGE2 + 16384 : st * STAGE + a1bytes),
              second ? sc->u + ((size_t)(36 * r + kb2_order(i)) * D_ + d2) * 128 : sc->h3 + ((size_t)(i * 18 + (d1 >> 5)) << 12), bytes, lb);
    };
    if (wp == 8) {
      int st = rows ? 4 : 0, ph = 1;
#pragma unroll 1
      for (int kb = st; kb < 32; kb++) {
        if (rows && (kb >> 1) == 2) mbar_wait(full0 + 8 * (B_S4 - 4 + kb), 0);
        mbar_wait(empty0 + 8 * st, ph);
        if (elect()) {
          load_a1(st, kb);
        }
        __syncwarp();
        ring_next<false>(st, ph);
      }
      if (g2) {
        st++;
#pragma unroll 1
        for (int i = 0; i < 36; i++) {
          if (i == HOLDA) mbar_wait(full0 + 8 * B_GO, 0);
          mbar_wait(empty0 + 8 * st, ph);
          if (elect()) {
            mbar_expect(full0 + 8 * st, 16384);
            tma3d_ef(sbase + st * STAGE2, &maps.w2, 64 * (36 * r + kb2_order(i)), s2 >> 6, full0 + 8 * st);
          }
          __syncwarp();
          ring_next<true>(st, ph);
        }
      }
    } else if (wp >= 10) {
      const int sw = wp - 10;
      if (sw) {
        if (rows) {
          bar_sync(8, 288);
          mbar_wait(full0 + 8 * H3W, 0);
          if (elect()) mbar_arrive(full0 + 8 * B_S4);
          bar_sync(9, 288);
          if (elect()) tma_st3d(&maps.h3, sbase + O_B3 + 4608, 64 * (cta & 15), 18 * (cta >> 4), 1);
          bulk_commit_wait();
          if (elect()) {
            red_add(sc->cnt + C_H3 + (cta >> 4) + 8, 4);
            mbar_arrive(full0 + 8 * B_S5);
            TS(24);
            asm volatile("fence.acq_rel.gpu;" ::: "memory");
            red_add(&sc->cnt[C_X + 64], 1);
          }
          __syncwarp();
        }
        if (g2) {
          uint2 v[3];
          int it = 0;
          do {
#pragma unroll
            for (int i = 0; i < 3; i++) v[i] = ld_rlx2(sc->mod + 3 * D_ + d2 + 2 * min(l + 32 * i, 71));
          } while (any(or3(diff2(v[0].x, v[0].y, tag16), diff2(v[1].x, v[1].y, tag16), diff2(v[2].x, v[2].y, tag16)) & 0xffffu) && ++it < SPIN_MAX);
#pragma unroll
          for (int i = 0; i < 3; i++) sts(sbase + O_GB + 4 * min(l + 32 * i, 71), __byte_perm(v[i].x, v[i].y, 0x7632));
          __syncwarp();
        }
        wait_cnt<true>(&sc->cnt[C_X + 64], 128 * ep);
        if (elect()) mbar_arrive(full0 + 8 * B_X);
        __syncwarp();
      }
      uint32_t lph = 0;
      auto check_tiles = [&](bool second, int n, int st, uint32_t o1, uint32_t d2nd) {
        const uint32_t b1 = pin(sbase + o1), b2 = pin(sbase + o1 + d2nd);
        int i = 0, it = 0;
#pragma unroll 1
        do {
          const uint32_t so = st * (second ? STAGE2 : STAGE);
          mbar_wait(full0 + 8 * (B_LAND + st), (lph >> st) & 1);
          lph ^= 1u << st;
          uint32_t v[20];
#pragma unroll
          for (int k = 0; k < 20; k++) if (!second || k < 10 || k >= 12) v[k] = lds(k < 12 ? b1 + so + k * 1024 : b2 + so + (k - 12) * 1024); else v[k] = tag1;
#pragma unroll
          for (int k = 0; k < 10; k++) v[k] = diff2(v[2 * k], v[2 * k + 1], tag1);
          const uint32_t bad = or3(or3(or3(v[0], v[1], v[2]), or3(v[3], v[4], v[5]), v[6]), v[7], or3(v[8], v[9], 0));
          if (__builtin_expect(any(bad & 1) && ++it < SPIN_MAX, 0)) {
            FAILCNT(2 + second);
            fence_async_smem();
            __syncwarp();
            if (elect()) load_b(second, i, st);
            __syncwarp();
            continue;
          }
          if (elect()) mbar_arrive(full0 + 8 * st);
          if (++st == NST) st = 0;
          i++;
        } while (i < n);
      };
      if (!sw) check_tiles(false, NV1, 0, a1bytes + l * 32 + (l >> 2) * 4, helper ? 4096 : 12288);
      if (sw) {
#pragma unroll 1
        for (int k = 0; k < 2; k++) {
          bar_sync(13 + k, 160);
          if (helper || (first && !k)) continue;
          const uint32_t stg = sbase + (k ? O_U1 : ST0 * STAGE);
          const int kb = (f1 >> 6) + (k ^ flip);
          uint8_t* const ug = sc->u + ((size_t)kb * D_ + d1) * 128;
          if (g2) mbar_wait(full0 + 8 * B_GO, 0);
          if (first) pause(10 * TRK0);
#pragma unroll 1
          for (int i = 0; i < 20480; i += 2048) {
            if (elect()) bulk_st(ug + i, stg + i, 2048);
            pause(k ? TRKC : TRK0);
          }
          if (elect()) red_add(sc->cnt + C_U + kb2_pos(kb), 4);
          bulk_commit_wait();
          if (elect()) { if (!k) mbar_arrive(empty0 + 8 * ST0); TS(k ? 23 : 17); }
          __syncwarp();
        }
        if (elect()) { asm volatile("fence.acq_rel.gpu;" ::: "memory"); red_add(&sc->cnt[C_X], 1); }
        __syncwarp();
      }
      if (g2) {
        if (!sw) check_tiles(true, NV2, 3, 16384 + l * 32 + g * 4, 10240);
        else {
          wait_cnt<true>(&sc->cnt[C_X], NCTA * ep);
          if (elect()) mbar_arrive(full0 + 8 * B_X);
          if (cta == 0) sc->cnt[C_EP + (pin(l) ^ 1)] = ep;
          __syncwarp();
        }
      }
      __syncwarp();
    } else {
      uint32_t ready = 0;
      int st = 0, ph = 1;
#pragma unroll 1
      for (int kb = 0; kb < 32; kb++) {
        const uint8_t* src = upin(sc->h3 + ((size_t)(kb * 18 + (d1 >> 5)) << 12));
        const uint32_t dst = upin(sbase + st * STAGE + a1bytes), lb = full0 + 8 * ((kb < NV1 ? B_LAND : 0) + st);
        if (kb == NV1) { mbar_wait(full0 + 8 * B_X, 0); fence_async_glb(); ready = ~0u; }
        if (rows && (kb >> 1) == 2) mbar_wait(full0 + 8 * (B_S4 - 4 + kb), 0);
        mbar_wait(empty0 + 8 * st, ph);
        if (elect()) mbar_expect(lb, STAGE - a1bytes);
        wait_flags(sc->cnt + C_H3 + l, (kb & 7) + (kb < 8 ? 0 : 8), 64 * ep - 24 * STRESS, ready);
        if (elect()) bulk_ld(dst, src, STAGE - a1bytes, lb);
        ring_next<false>(st, ph);
      }
      if (g2) {
        ready = 0;
        st++;
#pragma unroll 1
        for (int i = 0; i < 36; i++) {
          const int kb = kb2_order(i);
          const uint8_t* src = upin(sc->u + ((size_t)(36 * r + kb) * D_ + d2) * 128);
          const uint32_t dst = upin(sbase + st * STAGE2 + 16384), lb = full0 + 8 * ((i < NV2 ? B_LAND : 0) + st);
          if (i == NV2) { mbar_wait(full0 + 8 * B_X, 1); fence_async_glb(); ready = ~0u; }
          mbar_wait(empty0 + 8 * st, ph);
          if (elect()) mbar_expect(lb, 18432);
          wait_flags(sc->cnt + C_U + 64 * r + l, i & 31, 16 * ep - 8 * STRESS, ready);
          if (elect()) {
            bulk_ld(dst, src, 18432, lb);
            if (i == GOAT) mbar_arrive(full0 + 8 * B_GO);
          }
          ring_next<true>(st, ph);
        }
      }
    }
  } else {
    asm volatile("setmaxnreg.inc.sync.aligned.u32 232;");
    const int wgu = wg;
    constexpr uint32_t sb4 = sbase >> 4;
    const int w = wp & 3;
    Ring rg = {0, 0};
    uint32_t* const x1p = p.out + (size_t)(cta + 128 * ((wp & 3) + 8 * wg)) * 288 + l;
    const int direct = helper || (first && !wg), kbA = (f1 >> 6) + (helper ? 2 : 1) * (wg ^ flip), kbB = (f1 >> 6) + 1;
    const uint32_t uo = (t >> 1) * 2048 + (16 * w + g) * 32 + (((t ^ (g >> 2)) & 1) << 4);
    const uint32_t ad = pin(sbase + (wg ? O_U1 : ST0 * STAGE) + uo);
    uint8_t* const ug0 = pin(sc->u + ((size_t)kbA * D_ + d1) * 128 + uo);
    const int ud1 = upin(helper ? (kbB - kbA) * (D_ * 128) - 3 * 4096 : 0);
    const bool utg = ((t ^ (g >> 2) ^ w) & 1) == 0;
    const uint32_t um0 = pin(utg && g < 4 ? ~1u : ~0u), um1 = pin(utg && g >= 4 ? ~1u : ~0u);
    float acc[96];
    constexpr uint32_t LA = (8192 >> 4) << 16, LB = (4096 >> 4) << 16;
    {
      const float a0 = 0.5f * bf_lo(pin(bia[0])), a1 = 0.5f * bf_lo(pin(bia[1])), b0 = 0.5f * bf_lo(pin(bia[2])), b1 = 0.5f * bf_lo(pin(bia[3]));
#pragma unroll
      for (int i = 0; i < 96; i++) acc[i] = i < 48 ? ((i & 2) ? a1 : a0) : ((i & 2) ? b1 : b0);
      reg_fence(acc);
    }
    if (!helper) gemm_main<0>(acc, sb4 + (wgu ^ flip) * 512 + LA, 0, sb4 + 1024 + LB, wgu, rg, rows, first ? NST : NST - 1, x1p, xr);
    else {
      float ac2[96];
#pragma unroll
      for (int i = 0; i < 96; i++) asm volatile("mov.b32 %0, %1;" : "=f"(ac2[i]) : "f"(acc[i]));
      gemm_main<1>(ac2, sb4 + (wgu ^ flip) * 1024 + LA, sb4 + 512 + LA, sb4 + 1536 + LB, wgu, rg, rows, NST - 1, x1p, xr);
#pragma unroll
      for (int i = 0; i < 96; i++) asm volatile("mov.b32 %0, %1;" : "=f"(acc[i]) : "f"(ac2[i]));
    }
    if (t128 == 0) { TS(wg ? 16 : 6); if (wg) TSC(5); }
    {
      float tp[2] = {0.f, 0.f};
#pragma unroll
      for (int j = 0; j < 12; j++) {
        const float* a = &acc[16 * (j >> 1) + 2 * (j & 1)];
        const float k3 = j < 2 ? GK3 : fmaf(tp[j & 1], 0.0f, GK3);
        uint32_t o[4];
#pragma unroll
        for (int e = 0; e < 4; e++) {
          const float h0 = a[4 * e], h1 = a[4 * e + 1];
          float z0 = h0 * fmaf(h0 * k3, h0, GK1), z1 = h1 * fmaf(h1 * k3, h1, GK1);
          asm("tanh.approx.f32 %0, %0;" : "+f"(z0));
          asm("tanh.approx.f32 %0, %0;" : "+f"(z1));
          if (e == GDEP) tp[j & 1] = z0;
          o[e] = pack_bf16(fmaf(h0, z0, h0), fmaf(h1, z1, h1));
          if ((e >> 1) == (j & 1)) o[e] = bitsel(o[e], (e & 1) ? um1 : um0, tag1);
        }
        asm volatile("{\n.reg .pred p;\nsetp.ne.u32 p, %6, 0;\n@p st.global.v4.b32 [%0], {%2,%3,%4,%5};\n@!p st.shared.v4.b32 [%1], {%2,%3,%4,%5};\n}"
                     ::"l"(ug0 + (j < 6 ? 0 : ud1) + (j >> 1) * 4096 + (j & 1) * 256), "r"(ad + (j >> 1) * 4096 + (j & 1) * 256),
                       "r"(o[0]), "r"(o[1]), "r"(o[2]), "r"(o[3]), "r"(direct) : "memory");
        if ((j == 5 && helper && !wgu) || (j == 9 && !helper)) break;
      }
      if (!direct) fence_async_smem();
      else if (elect()) {
        red_add(sc->cnt + C_U + kb2_pos(kbA), 1);
        if (wgu) red_add(sc->cnt + C_U + kb2_pos(kbB), 1);
      }
      __syncwarp();
      bar_arrive(13 + wgu, 160);
      if (t128 == 0) TS(wg ? 29 : 28);
    }
    if (g2) {
      const int mb = wgu ^ r;
      const int odd = z2 & 1;
      uint4 gq[4];
      uint2 gs;
      {
        float a0 = 0.f, a1 = 0.f;
        if (wgu) { a0 = __bfloat162float(p.b2[s2 + 64 * mb + 16 * w + g]); a1 = __bfloat162float(p.b2[s2 + 64 * mb + 16 * w + 8 + g]); }
#pragma unroll
        for (int i = 0; i < 4; i++) gq[i] = lds4(sbase + O_GB + 32 * odd + 64 * i + 16 * t);
        gs = lds2(sbase + O_GB + (odd ? 0 : 256) + 8 * t);
#pragma unroll
        for (int i = 0; i < 72; i++) acc[i] = (i & 2) ? a1 : a0;
      }
      uint32_t* const ob = p.out + (size_t)(s2 + 64 * mb + 16 * w + g) * 288 + (d2 >> 1);
      uint32_t* const oq = pin(ob + 8 * odd + 4 * t);
      uint32_t* const os = pin(ob + (odd ? 0 : 64) + 2 * t);
      rg.st++;
      gemm_main<3>(acc, sb4 + mb * 512 + LA, 0, sb4 + 1024 + ((2048 >> 4) << 16), wgu, rg, rows, NST, x1p, xr);
      if (t128 == 0) { TS(wg ? 20 : 19); if (wg) TSC(22); }
      auto finish = [&](const float* aq, const float* as) {
#pragma unroll
        for (int i = 0; i < 8; i++) {
          const float* a = aq + 16 * (i >> 1) + 2 * (i & 1);
          const uint4 gv = gq[i >> 1];
          red_bf16x8(oq + (i & 1) * 2304 + 16 * (i >> 1), hmul2(gv.x, pack_bf16(a[0], a[1])), hmul2(gv.y, pack_bf16(a[4], a[5])),
                     hmul2(gv.z, pack_bf16(a[8], a[9])), hmul2(gv.w, pack_bf16(a[12], a[13])));
        }
#pragma unroll
        for (int i = 0; i < 2; i++) red_bf16x4(os + i * 2304, hmul2(gs.x, pack_bf16(as[2 * i], as[2 * i + 1])), hmul2(gs.y, pack_bf16(as[2 * i + 4], as[2 * i + 5])));
      };
      if (odd) finish(&acc[8], &acc[0]); else finish(&acc[0], &acc[64]);
      if (t128 == 0) TS(wg ? 7 : 21);
      __syncwarp();
    }
  }
}

typedef CUresult (*EncodeFn)(CUtensorMap*, CUtensorMapDataType, cuuint32_t, void*, const cuuint64_t*, const cuuint64_t*, const cuuint32_t*,
                             const cuuint32_t*, CUtensorMapInterleave, CUtensorMapSwizzle, CUtensorMapL2promotion, CUtensorMapFloatOOBfill);

struct Dim { cuuint64_t n, stride; cuuint32_t box; };
template <int RANK>
void make_map(EncodeFn enc, CUtensorMap* m, bool words, int swz, const void* ptr, const Dim (&d)[RANK]) {
  cuuint64_t gd[RANK], gs[RANK];
  cuuint32_t bx[RANK], es[RANK];
  for (int i = 0; i < RANK; i++) { gd[i] = d[i].n; gs[i] = d[i].stride; bx[i] = d[i].box; es[i] = 1; }
  enc(m, words ? CU_TENSOR_MAP_DATA_TYPE_UINT32 : CU_TENSOR_MAP_DATA_TYPE_BFLOAT16, RANK, const_cast<void*>(ptr), gd, gs + 1, bx, es,
      CU_TENSOR_MAP_INTERLEAVE_NONE, static_cast<CUtensorMapSwizzle>(swz),
      swz == 3 ? CU_TENSOR_MAP_L2_PROMOTION_L2_256B : CU_TENSOR_MAP_L2_PROMOTION_NONE, CU_TENSOR_MAP_FLOAT_OOB_FILL_NONE);
}

}

extern "C" void kernel_launch(void* const* d_in, const int* in_sizes, int n_in, void* d_out, int out_size) {
  (void)in_sizes; (void)n_in; (void)out_size;
  static EncodeFn enc = nullptr;
  static void *sptr = nullptr, *tptr = nullptr;
  if (!enc) {
    void* f = nullptr; cudaDriverEntryPointQueryResult qr;
    cudaGetDriverEntryPoint("cuTensorMapEncodeTiled", &f, cudaEnableDefault, &qr);
    enc = reinterpret_cast<EncodeFn>(f);
    cudaFuncSetAttribute(fused_kernel, cudaFuncAttributeMaxDynamicSharedMemorySize, SMEM_BYTES);
    cudaGetSymbolAddress(&sptr, g_s);
    cudaGetSymbolAddress(&tptr, T_TAB);
  }
  Params p;
  p.x = (const __nv_bfloat16*)d_in[0]; p.wr = (const __nv_bfloat16*)d_in[1]; p.wi = (const __nv_bfloat16*)d_in[2];
  p.b1 = (const __nv_bfloat16*)d_in[5]; p.b2 = (const __nv_bfloat16*)d_in[7];
  p.c = (const __nv_bfloat16*)d_in[8]; p.wmod = (const __nv_bfloat16*)d_in[9];
  p.w1 = (const __nv_bfloat16*)d_in[4]; p.w2 = (const __nv_bfloat16*)d_in[6];
  p.out = static_cast<uint32_t*>(d_out); p.s = static_cast<Scratch*>(sptr); p.tab = static_cast<const uint4*>(tptr);
  Maps maps;
  make_map<4>(enc, &maps.w1a, false, 3, p.w1, {{64, 0, 64}, {16, 128 * 2 * F_, 4}, {128, 2 * F_, 16}, {72, 128, 2}});
  make_map<4>(enc, &maps.w1b, false, 3, p.w1, {{64, 0, 64}, {16, 128 * 2 * F_, 4}, {128, 2 * F_, 16}, {72, 128, 3}});
  make_map<3>(enc, &maps.w2, false, 3, p.w2, {{64, 0, 64}, {F_, 2 * S_, 64}, {32, 128, 2}});
  make_map<2>(enc, &maps.z1, true, 0, p.s->z1, {{5120, 0, 40}, {120, 20480, 60}});
  for (int i = 0; i < 2; i++) make_map<2>(enc, &maps.z2[i], true, 0, p.s->z2, {{4800, 0, i ? 16u : 24u}, {128, 19200, 128}});
  for (int i = 0; i < 4; i++) make_map<2>(enc, &maps.wf[i], false, 2 - (i & 1), (i & 2) ? p.wi : p.wr, {{16 * DF_, 0, (i & 1) ? 16u : 32u}, {128, 32 * DF_, 128}});
  make_map<2>(enc, &maps.wm, false, 1, p.wmod, {{6 * D_, 0, 16}, {D_, 12 * D_, 192}});
  make_map<3>(enc, &maps.h3, true, 0, p.s->h3, {{1024, 0, 64}, {144, 4096, 18}, {4, 144 * 4096, 3}});
  fused_kernel<<<NCTA, NTHR, SMEM_BYTES, cudaStreamPerThread>>>(p, maps);
}
```

```cpp
#include <cuda_runtime.h>
#include <cuda_bf16.h>
#include <cuda.h>
#include <stdint.h>

namespace {

constexpr int S_ = 2048, D_ = 576, DF_ = 289, F_ = 4608;
constexpr int NCTA = 132, NTHR = 384;
constexpr int STAGE = 36864, NST = 6;
constexpr int STAGE2 = 34816, O_U1 = NST * STAGE2, O_GB = O_U1 + 20480, SMEM_BYTES = 232448;
constexpr uint32_t sbase = 1024, red = sbase + NST * STAGE, full0 = sbase + SMEM_BYTES - 256, empty0 = full0 + 8 * NST;
constexpr int O_NRM = 0, O_B1 = 19456, O_Z1 = 38912, O_P2 = 59392, O_ST = 3 * STAGE;
constexpr int O_RAW = 4 * STAGE;
constexpr int O_IN = 4 * STAGE, O_Y = O_IN + 19456, O_B3 = O_IN + 38912, O_MOD = O_IN + 57344;

__device__ __align__(128) const uint32_t T_TAB[5632] = {
0x3f803f80,0xbf803f80,0x3f803f80,0xbf803f80,0x3f803f80,0xbf803f80,0x3f803f80,0xbf803f80,0x3f803f80,0xbf803f80,0x3f803f80,0xbf803f80,
0x3f803f80,0xbf803f80,0x3f803f80,0xbf803f80,0x3f7f3f80,0xbdc90000,0x3f223f35,0xbf46bf35,0x3f753f7b,0xbe95be48,0x3ef13f0e,0xbf62bf55,
0x3f623f6d,0xbef1bec4,0x3e953ec4,0xbf75bf6d,0x3f463f55,0xbf22bf0e,0x3dc93e48,0xbf7fbf7b,0x3f7b3f80,0xbe480000,0xbe480000,0xbf7bbf80,
0x3f553f6d,0xbf0ebec4,0xbf0ebec4,0xbf55bf6d,0x3f0e3f35,0xbf55bf35,0xbf55bf35,0xbf0ebf35,0x3e483ec4,0xbf7bbf6d,0xbf7bbf6d,0xbe48bec4,
0x3f753f80,0xbe950000,0xbf62bf35,0xbef1bf35,0x3f223f55,0xbf46bf0e,0xbf7fbf7b,0x3dc9be48,0x3dc93ec4,0xbf7fbf6d,0xbf46bf6d,0x3f223ec4,
0xbef1be48,0xbf62bf7b,0xbe95bf0e,0x3f753f55,0x3f6d3f80,0xbec40000,0xbf6dbf80,0x3ec40000,0x3ec43f35,0xbf6dbf35,0xbec4bf35,0x3f6d3f35,
0xbec40000,0xbf6dbf80,0x3ec40000,0x3f6d3f80,0xbf6dbf35,0xbec4bf35,0x3f6d3f35,0x3ec43f35,0x3f623f80,0xbef10000,0xbe95bf35,0x3f753f35,
0x3dc93f0e,0xbf7fbf55,0x3f223e48,0x3f463f7b,0xbf46bec4,0xbf22bf6d,0x3f7f3f6d,0xbdc93ec4,0xbf75bf7b,0x3e95be48,0x3ef13f55,0xbf62bf0e,
0x3f553f80,0xbf0e0000,0x3f0e0000,0x3f553f80,0xbe483ec4,0xbf7bbf6d,0x3f7b3f6d,0xbe483ec4,0xbf7bbf35,0xbe48bf35,0x3e483f35,0xbf7bbf35,
0xbf0ebf6d,0x3f553ec4,0xbf55bec4,0xbf0ebf6d,0x3f463f80,0xbf220000,0x3f7f3f35,0x3dc93f35,0xbef13e48,0xbf62bf7b,0x3e953f55,0xbf75bf0e,
0xbf75bf6d,0x3e95bec4,0xbf62bec4,0xbef1bf6d,0x3dc9bf0e,0x3f7f3f55,0xbf22bf7b,0x3f463e48,0x3f353f80,0xbf350000,0x3f353f80,0xbf350000,
0xbf350000,0xbf35bf80,0xbf350000,0xbf35bf80,0xbf35bf80,0x3f350000,0xbf35bf80,0x3f350000,0x3f350000,0x3f353f80,0x3f350000,0x3f353f80,
0x3f223f80,0xbf460000,0xbdc93f35,0xbf7fbf35,0xbf62be48,0xbef1bf7b,0xbf75bf55,0x3e95bf0e,0xbe95bf6d,0x3f753ec4,0x3ef1bec4,0x3f623f6d,
0x3f7f3f0e,0x3dc93f55,0x3f463f7b,0xbf223e48,0x3f0e3f80,0xbf550000,0xbf550000,0xbf0ebf80,0xbf7bbec4,0xbe48bf6d,0xbe48bf6d,0x3f7b3ec4,
0x3e48bf35,0x3f7b3f35,0x3f7b3f35,0xbe483f35,0x3f553f6d,0xbf0e3ec4,0xbf0e3ec4,0xbf55bf6d,0x3ef13f80,0xbf620000,0xbf75bf35,0x3e95bf35,
0xbf7fbf0e,0x3dc9bf55,0x3f46be48,0x3f223f7b,0x3f22bec4,0x3f463f6d,0x3dc93f6d,0xbf7fbec4,0x3e953f7b,0xbf75be48,0xbf62bf55,0x3ef1bf0e,
0x3ec43f80,0xbf6d0000,0xbec4bf80,0x3f6d0000,0xbf6dbf35,0x3ec4bf35,0x3f6d3f35,0xbec43f35,0x3f6d0000,0x3ec43f80,0xbf6d0000,0xbec4bf80,
0xbec43f35,0xbf6dbf35,0x3ec4bf35,0x3f6d3f35,0x3e953f80,0xbf750000,0x3ef1bf35,0x3f623f35,0xbf46bf55,0x3f22bf0e,0x3dc93f7b,0xbf7fbe48,
0x3f7f3ec4,0xbdc93f6d,0xbf22bf6d,0x3f46bec4,0xbf623e48,0xbef1bf7b,0x3f753f0e,0xbe953f55,0x3e483f80,0xbf7b0000,0x3f7b0000,0x3e483f80,
0xbf0ebf6d,0x3f55bec4,0xbf553ec4,0xbf0ebf6d,0x3f553f35,0xbf0e3f35,0x3f0ebf35,0x3f553f35,0xbf7bbec4,0x3e48bf6d,0xbe483f6d,0xbf7bbec4,
0x3dc93f80,0xbf7f0000,0x3f463f35,0xbf223f35,0xbe95bf7b,0x3f75be48,0xbf62bf0e,0x3ef1bf55,0x3ef13f6d,0xbf623ec4,0x3f753ec4,0xbe953f6d,
0xbf22bf55,0x3f46bf0e,0xbf7fbe48,0x3dc9bf7b,0x3f80,0xbf800000,0x3f80,0xbf800000,0xbf80,0x3f800000,0xbf80,0x3f800000,
0x3f80,0xbf800000,0x3f80,0xbf800000,0xbf80,0x3f800000,0xbf80,0x3f800000,0xbdc93f80,0xbf7f0000,0xbf463f35,0xbf22bf35,
0x3e95bf7b,0x3f753e48,0x3f62bf0e,0x3ef13f55,0xbef13f6d,0xbf62bec4,0xbf753ec4,0xbe95bf6d,0x3f22bf55,0x3f463f0e,0x3f7fbe48,0x3dc93f7b,
0xbe483f80,0xbf7b0000,0xbf7b0000,0x3e48bf80,0x3f0ebf6d,0x3f553ec4,0x3f553ec4,0xbf0e3f6d,0xbf553f35,0xbf0ebf35,0xbf0ebf35,0x3f55bf35,
0x3f7bbec4,0x3e483f6d,0x3e483f6d,0xbf7b3ec4,0xbe953f80,0xbf750000,0xbef1bf35,0x3f62bf35,0x3f46bf55,0x3f223f0e,0xbdc93f7b,0xbf7f3e48,
0xbf7f3ec4,0xbdc9bf6d,0x3f22bf6d,0x3f463ec4,0x3f623e48,0xbef13f7b,0xbf753f0e,0xbe95bf55,0xbec43f80,0xbf6d0000,0x3ec4bf80,0x3f6d0000,
0x3f6dbf35,0x3ec43f35,0xbf6d3f35,0xbec4bf35,0xbf6d0000,0x3ec4bf80,0x3f6d0000,0xbec43f80,0x3ec43f35,0xbf6d3f35,0xbec4bf35,0x3f6dbf35,
0xbef13f80,0xbf620000,0x3f75bf35,0x3e953f35,0x3f7fbf0e,0x3dc93f55,0xbf46be48,0x3f22bf7b,0xbf22bec4,0x3f46bf6d,0xbdc93f6d,0xbf7f3ec4,
0xbe953f7b,0xbf753e48,0x3f62bf55,0x3ef13f0e,0xbf0e3f80,0xbf550000,0x3f550000,0xbf0e3f80,0x3f7bbec4,0xbe483f6d,0x3e48bf6d,0x3f7bbec4,
0xbe48bf35,0x3f7bbf35,0xbf7b3f35,0xbe48bf35,0xbf553f6d,0xbf0ebec4,0x3f0e3ec4,0xbf553f6d,0xbf223f80,0xbf460000,0x3dc93f35,0xbf7f3f35,
0x3f62be48,0xbef13f7b,0x3f75bf55,0x3e953f0e,0x3e95bf6d,0x3f75bec4,0xbef1bec4,0x3f62bf6d,0xbf7f3f0e,0x3dc9bf55,0xbf463f7b,0xbf22be48,
0xbf353f80,0xbf350000,0xbf353f80,0xbf350000,0x3f350000,0xbf353f80,0x3f350000,0xbf353f80,0x3f35bf80,0x3f350000,0x3f35bf80,0x3f350000,
0xbf350000,0x3f35bf80,0xbf350000,0x3f35bf80,0xbf463f80,0xbf220000,0xbf7f3f35,0x3dc9bf35,0x3ef13e48,0xbf623f7b,0xbe953f55,0xbf753f0e,
0x3f75bf6d,0x3e953ec4,0x3f62bec4,0xbef13f6d,0xbdc9bf0e,0x3f7fbf55,0x3f22bf7b,0x3f46be48,0xbf553f80,0xbf0e0000,0xbf0e0000,0x3f55bf80,
0x3e483ec4,0xbf7b3f6d,0xbf7b3f6d,0xbe48bec4,0x3f7bbf35,0xbe483f35,0xbe483f35,0xbf7b3f35,0x3f0ebf6d,0x3f55bec4,0x3f55bec4,0xbf0e3f6d,
0xbf623f80,0xbef10000,0x3e95bf35,0x3f75bf35,0xbdc93f0e,0xbf7f3f55,0xbf223e48,0x3f46bf7b,0x3f46bec4,0xbf223f6d,0xbf7f3f6d,0xbdc9bec4,
0x3f75bf7b,0x3e953e48,0xbef13f55,0xbf623f0e,0xbf6d3f80,0xbec40000,0x3f6dbf80,0x3ec40000,0xbec43f35,0xbf6d3f35,0x3ec4bf35,0x3f6dbf35,
0x3ec40000,0xbf6d3f80,0xbec40000,0x3f6dbf80,0x3f6dbf35,0xbec43f35,0xbf6d3f35,0x3ec4bf35,0xbf753f80,0xbe950000,0x3f62bf35,0xbef13f35,
0xbf223f55,0xbf463f0e,0x3f7fbf7b,0x3dc93e48,0xbdc93ec4,0xbf7f3f6d,0x3f46bf6d,0x3f22bec4,0x3ef1be48,0xbf623f7b,0x3e95bf0e,0x3f75bf55,
0xbf7b3f80,0xbe480000,0x3e480000,0xbf7b3f80,0xbf553f6d,0xbf0e3ec4,0x3f0ebec4,0xbf553f6d,0xbf0e3f35,0xbf553f35,0x3f55bf35,0xbf0e3f35,
0xbe483ec4,0xbf7b3f6d,0x3f7bbf6d,0xbe483ec4,0xbf7f3f80,0xbdc90000,0xbf223f35,0xbf463f35,0xbf753f7b,0xbe953e48,0xbef13f0e,0xbf623f55,
0xbf623f6d,0xbef13ec4,0xbe953ec4,0xbf753f6d,0xbf463f55,0xbf223f0e,0xbdc93e48,0xbf7f3f7b,0x3f803f80,0xbf803f80,0x3f803f80,0xbf803f80,
0x3f803f80,0xbf803f80,0x3f803f80,0xbf803f80,0x3f803f80,0xbf803f80,0x3f803f80,0xbf803f80,0x3f803f80,0xbf803f80,0x3f803f80,0xbf803f80,
0xbdc90000,0xbf7fbf80,0xbf46bf35,0xbf22bf35,0xbe95be48,0xbf75bf7b,0xbf62bf55,0xbef1bf0e,0xbef1bec4,0xbf62bf6d,0xbf75bf6d,0xbe95bec4,
0xbf22bf0e,0xbf46bf55,0xbf7fbf7b,0xbdc9be48,0xbf7bbf80,0x3e480000,0x3e480000,0x3f7b3f80,0xbf55bf6d,0x3f0e3ec4,0x3f0e3ec4,0x3f553f6d,
0xbf0ebf35,0x3f553f35,0x3f553f35,0x3f0e3f35,0xbe48bec4,0x3f7b3f6d,0x3f7b3f6d,0x3e483ec4,0x3e950000,0x3f753f80,0x3ef13f35,0xbf62bf35,
0x3f463f0e,0x3f223f55,0xbdc93e48,0xbf7fbf7b,0x3f7f3f6d,0x3dc93ec4,0xbf22bec4,0xbf46bf6d,0x3f623f7b,0xbef1be48,0xbf75bf55,0xbe95bf0e,
0x3f6d3f80,0xbec40000,0xbf6dbf80,0x3ec40000,0x3ec43f35,0xbf6dbf35,0xbec4bf35,0x3f6d3f35,0xbec40000,0xbf6dbf80,0x3ec40000,0x3f6d3f80,
0xbf6dbf35,0xbec4bf35,0x3f6d3f35,0x3ec43f35,0xbef10000,0xbf62bf80,0x3f753f35,0x3e953f35,0xbf7fbf55,0xbdc9bf0e,0x3f463f7b,0xbf22be48,
0xbf22bf6d,0x3f463ec4,0xbdc93ec4,0xbf7fbf6d,0x3e95be48,0x3f753f7b,0xbf62bf0e,0xbef1bf55,0xbf55bf80,0x3f0e0000,0xbf0e0000,0xbf55bf80,
0x3e48bec4,0x3f7b3f6d,0xbf7bbf6d,0x3e48bec4,0x3f7b3f35,0x3e483f35,0xbe48bf35,0x3f7b3f35,0x3f0e3f6d,0xbf55bec4,0x3f553ec4,0x3f0e3f6d,
0x3f220000,0x3f463f80,0xbdc9bf35,0x3f7f3f35,0x3f623f7b,0xbef13e48,0x3f753f0e,0x3e953f55,0xbe953ec4,0xbf75bf6d,0x3ef13f6d,0xbf62bec4,
0xbf7fbf55,0x3dc9bf0e,0xbf46be48,0xbf22bf7b,0x3f353f80,0xbf350000,0x3f353f80,0xbf350000,0xbf350000,0xbf35bf80,0xbf350000,0xbf35bf80,
0xbf35bf80,0x3f350000,0xbf35bf80,0x3f350000,0x3f350000,0x3f353f80,0x3f350000,0x3f353f80,0xbf460000,0xbf22bf80,0xbf7fbf35,0x3dc9bf35,
0xbef1bf7b,0x3f623e48,0x3e95bf0e,0x3f753f55,0x3f753ec4,0x3e953f6d,0x3f623f6d,0xbef13ec4,0x3dc93f55,0xbf7fbf0e,0xbf223e48,0xbf46bf7b,
0xbf0ebf80,0x3f550000,0x3f550000,0x3f0e3f80,0x3f7b3ec4,0x3e483f6d,0x3e483f6d,0xbf7bbec4,0xbe483f35,0xbf7bbf35,0xbf7bbf35,0x3e48bf35,
0xbf55bf6d,0x3f0ebec4,0x3f0ebec4,0x3f553f6d,0x3f620000,0x3ef13f80,0xbe953f35,0xbf75bf35,0xbdc93f55,0xbf7fbf0e,0xbf22bf7b,0x3f46be48,
0xbf46bf6d,0x3f22bec4,0x3f7f3ec4,0x3dc93f6d,0x3f753e48,0x3e953f7b,0xbef13f0e,0xbf62bf55,0x3ec43f80,0xbf6d0000,0xbec4bf80,0x3f6d0000,
0xbf6dbf35,0x3ec4bf35,0x3f6d3f35,0xbec43f35,0x3f6d0000,0x3ec43f80,0xbf6d0000,0xbec4bf80,0xbec43f35,0xbf6dbf35,0x3ec4bf35,0x3f6d3f35,
0xbf750000,0xbe95bf80,0x3f623f35,0xbef13f35,0x3f22bf0e,0x3f463f55,0xbf7fbe48,0xbdc9bf7b,0xbdc93f6d,0xbf7fbec4,0x3f46bec4,0x3f223f6d,
0xbef1bf7b,0x3f62be48,0xbe953f55,0xbf75bf0e,0xbe48bf80,0x3f7b0000,0xbf7b0000,0xbe48bf80,0x3f0e3f6d,0xbf553ec4,0x3f55bec4,0x3f0e3f6d,
0xbf55bf35,0x3f0ebf35,0xbf0e3f35,0xbf55bf35,0x3f7b3ec4,0xbe483f6d,0x3e48bf6d,0x3f7b3ec4,0x3f7f0000,0x3dc93f80,0x3f22bf35,0x3f463f35,
0xbf753e48,0xbe95bf7b,0xbef13f55,0xbf62bf0e,0x3f62bec4,0x3ef13f6d,0x3e95bf6d,0x3f753ec4,0xbf463f0e,0xbf22bf55,0xbdc93f7b,0xbf7fbe48,
0x3f80,0xbf800000,0x3f80,0xbf800000,0xbf80,0x3f800000,0xbf80,0x3f800000,0x3f80,0xbf800000,0x3f80,0xbf800000,
0xbf80,0x3f800000,0xbf80,0x3f800000,0xbf7f0000,0x3dc9bf80,0xbf22bf35,0x3f46bf35,0x3f753e48,0xbe953f7b,0x3ef13f55,0xbf623f0e,
0xbf62bec4,0x3ef1bf6d,0xbe95bf6d,0x3f75bec4,0x3f463f0e,0xbf223f55,0x3dc93f7b,0xbf7f3e48,0x3e48bf80,0x3f7b0000,0x3f7b0000,0xbe483f80,
0xbf0e3f6d,0xbf55bec4,0xbf55bec4,0x3f0ebf6d,0x3f55bf35,0x3f0e3f35,0x3f0e3f35,0xbf553f35,0xbf7b3ec4,0xbe48bf6d,0xbe48bf6d,0x3f7bbec4,
0x3f750000,0xbe953f80,0xbf623f35,0xbef1bf35,0xbf22bf0e,0x3f46bf55,0x3f7fbe48,0xbdc93f7b,0x3dc93f6d,0xbf7f3ec4,0xbf46bec4,0x3f22bf6d,
0x3ef1bf7b,0x3f623e48,0x3e953f55,0xbf753f0e,0xbec43f80,0xbf6d0000,0x3ec4bf80,0x3f6d0000,0x3f6dbf35,0x3ec43f35,0xbf6d3f35,0xbec4bf35,
0xbf6d0000,0x3ec4bf80,0x3f6d0000,0xbec43f80,0x3ec43f35,0xbf6d3f35,0xbec4bf35,0x3f6dbf35,0xbf620000,0x3ef1bf80,0x3e953f35,0xbf753f35,
0x3dc93f55,0xbf7f3f0e,0x3f22bf7b,0x3f463e48,0x3f46bf6d,0x3f223ec4,0xbf7f3ec4,0x3dc9bf6d,0xbf753e48,0x3e95bf7b,0x3ef13f0e,0xbf623f55,
0x3f0ebf80,0x3f550000,0xbf550000,0x3f0ebf80,0xbf7b3ec4,0x3e48bf6d,0xbe483f6d,0xbf7b3ec4,0x3e483f35,0xbf7b3f35,0x3f7bbf35,0x3e483f35,
0x3f55bf6d,0x3f0e3ec4,0xbf0ebec4,0x3f55bf6d,0x3f460000,0xbf223f80,0x3f7fbf35,0x3dc93f35,0x3ef1bf7b,0x3f62be48,0xbe95bf0e,0x3f75bf55,
0xbf753ec4,0x3e95bf6d,0xbf623f6d,0xbef1bec4,0xbdc93f55,0xbf7f3f0e,0x3f223e48,0xbf463f7b,0xbf353f80,0xbf350000,0xbf353f80,0xbf350000,
0x3f350000,0xbf353f80,0x3f350000,0xbf353f80,0x3f35bf80,0x3f350000,0x3f35bf80,0x3f350000,0xbf350000,0x3f35bf80,0xbf350000,0x3f35bf80,
0xbf220000,0x3f46bf80,0x3dc9bf35,0x3f7fbf35,0xbf623f7b,0xbef1be48,0xbf753f0e,0x3e95bf55,0x3e953ec4,0xbf753f6d,0xbef13f6d,0xbf623ec4,
0x3f7fbf55,0x3dc93f0e,0x3f46be48,0xbf223f7b,0x3f55bf80,0x3f0e0000,0x3f0e0000,0xbf553f80,0xbe48bec4,0x3f7bbf6d,0x3f7bbf6d,0x3e483ec4,
0xbf7b3f35,0x3e48bf35,0x3e48bf35,0x3f7bbf35,0xbf0e3f6d,0xbf553ec4,0xbf553ec4,0x3f0ebf6d,0x3ef10000,0xbf623f80,0xbf753f35,0x3e95bf35,
0x3f7fbf55,0xbdc93f0e,0xbf463f7b,0xbf223e48,0x3f22bf6d,0x3f46bec4,0x3dc93ec4,0xbf7f3f6d,0xbe95be48,0x3f75bf7b,0x3f62bf0e,0xbef13f55,
0xbf6d3f80,0xbec40000,0x3f6dbf80,0x3ec40000,0xbec43f35,0xbf6d3f35,0x3ec4bf35,0x3f6dbf35,0x3ec40000,0xbf6d3f80,0xbec40000,0x3f6dbf80,
0x3f6dbf35,0xbec43f35,0xbf6d3f35,0x3ec4bf35,0xbe950000,0x3f75bf80,0xbef13f35,0xbf623f35,0xbf463f0e,0x3f22bf55,0x3dc93e48,0xbf7f3f7b,
0xbf7f3f6d,0x3dc9bec4,0x3f22bec4,0xbf463f6d,0xbf623f7b,0xbef13e48,0x3f75bf55,0xbe953f0e,0x3f7bbf80,0x3e480000,0xbe480000,0x3f7bbf80,
0x3f55bf6d,0x3f0ebec4,0xbf0e3ec4,0x3f55bf6d,0x3f0ebf35,0x3f55bf35,0xbf553f35,0x3f0ebf35,0x3e48bec4,0x3f7bbf6d,0xbf7b3f6d,0x3e48bec4,
0x3dc90000,0xbf7f3f80,0x3f46bf35,0xbf223f35,0x3e95be48,0xbf753f7b,0x3f62bf55,0xbef13f0e,0x3ef1bec4,0xbf623f6d,0x3f75bf6d,0xbe953ec4,
0x3f22bf0e,0xbf463f55,0x3f7fbf7b,0xbdc93e48,0x3f803f80,0xbf803f80,0x3f803f80,0xbf803f80,0x3f803f80,0xbf803f80,0x3f803f80,0xbf803f80,
0x3f803f80,0xbf803f80,0x3f803f80,0xbf803f80,0x3f803f80,0xbf803f80,0x3f803f80,0xbf803f80,0xbf7fbf80,0x3dc90000,0xbf22bf35,0x3f463f35,
0xbf75bf7b,0x3e953e48,0xbef1bf0e,0x3f623f55,0xbf62bf6d,0x3ef13ec4,0xbe95bec4,0x3f753f6d,0xbf46bf55,0x3f223f0e,0xbdc9be48,0x3f7f3f7b,
0x3f7b3f80,0xbe480000,0xbe480000,0xbf7bbf80,0x3f553f6d,0xbf0ebec4,0xbf0ebec4,0xbf55bf6d,0x3f0e3f35,0xbf55bf35,0xbf55bf35,0xbf0ebf35,
0x3e483ec4,0xbf7bbf6d,0xbf7bbf6d,0xbe48bec4,0xbf75bf80,0x3e950000,0x3f623f35,0x3ef13f35,0xbf22bf55,0x3f463f0e,0x3f7f3f7b,0xbdc93e48,
0xbdc9bec4,0x3f7f3f6d,0x3f463f6d,0xbf22bec4,0x3ef13e48,0x3f623f7b,0x3e953f0e,0xbf75bf55,0x3f6d3f80,0xbec40000,0xbf6dbf80,0x3ec40000,
0x3ec43f35,0xbf6dbf35,0xbec4bf35,0x3f6d3f35,0xbec40000,0xbf6dbf80,0x3ec40000,0x3f6d3f80,0xbf6dbf35,0xbec4bf35,0x3f6d3f35,0x3ec43f35,
0xbf62bf80,0x3ef10000,0x3e953f35,0xbf75bf35,0xbdc9bf0e,0x3f7f3f55,0xbf22be48,0xbf46bf7b,0x3f463ec4,0x3f223f6d,0xbf7fbf6d,0x3dc9bec4,
0x3f753f7b,0xbe953e48,0xbef1bf55,0x3f623f0e,0x3f553f80,0xbf0e0000,0x3f0e0000,0x3f553f80,0xbe483ec4,0xbf7bbf6d,0x3f7b3f6d,0xbe483ec4,
0xbf7bbf35,0xbe48bf35,0x3e483f35,0xbf7bbf35,0xbf0ebf6d,0x3f553ec4,0xbf55bec4,0xbf0ebf6d,0xbf46bf80,0x3f220000,0xbf7fbf35,0xbdc9bf35,
0x3ef1be48,0x3f623f7b,0xbe95bf55,0x3f753f0e,0x3f753f6d,0xbe953ec4,0x3f623ec4,0x3ef13f6d,0xbdc93f0e,0xbf7fbf55,0x3f223f7b,0xbf46be48,
0x3f353f80,0xbf350000,0x3f353f80,0xbf350000,0xbf350000,0xbf35bf80,0xbf350000,0xbf35bf80,0xbf35bf80,0x3f350000,0xbf35bf80,0x3f350000,
0x3f350000,0x3f353f80,0x3f350000,0x3f353f80,0xbf22bf80,0x3f460000,0x3dc9bf35,0x3f7f3f35,0x3f623e48,0x3ef13f7b,0x3f753f55,0xbe953f0e,
0x3e953f6d,0xbf75bec4,0xbef13ec4,0xbf62bf6d,0xbf7fbf0e,0xbdc9bf55,0xbf46bf7b,0x3f22be48,0x3f0e3f80,0xbf550000,0xbf550000,0xbf0ebf80,
0xbf7bbec4,0xbe48bf6d,0xbe48bf6d,0x3f7b3ec4,0x3e48bf35,0x3f7b3f35,0x3f7b3f35,0xbe483f35,0x3f553f6d,0xbf0e3ec4,0xbf0e3ec4,0xbf55bf6d,
0xbef1bf80,0x3f620000,0x3f753f35,0xbe953f35,0x3f7f3f0e,0xbdc93f55,0xbf463e48,0xbf22bf7b,0xbf223ec4,0xbf46bf6d,0xbdc9bf6d,0x3f7f3ec4,
0xbe95bf7b,0x3f753e48,0x3f623f55,0xbef13f0e,0x3ec43f80,0xbf6d0000,0xbec4bf80,0x3f6d0000,0xbf6dbf35,0x3ec4bf35,0x3f6d3f35,0xbec43f35,
0x3f6d0000,0x3ec43f80,0xbf6d0000,0xbec4bf80,0xbec43f35,0xbf6dbf35,0x3ec4bf35,0x3f6d3f35,0xbe95bf80,0x3f750000,0xbef13f35,0xbf62bf35,
0x3f463f55,0xbf223f0e,0xbdc9bf7b,0x3f7f3e48,0xbf7fbec4,0x3dc9bf6d,0x3f223f6d,0xbf463ec4,0x3f62be48,0x3ef13f7b,0xbf75bf0e,0x3e95bf55,
0x3e483f80,0xbf7b0000,0x3f7b0000,0x3e483f80,0xbf0ebf6d,0x3f55bec4,0xbf553ec4,0xbf0ebf6d,0x3f553f35,0xbf0e3f35,0x3f0ebf35,0x3f553f35,
0xbf7bbec4,0x3e48bf6d,0xbe483f6d,0xbf7bbec4,0xbdc9bf80,0x3f7f0000,0xbf46bf35,0x3f22bf35,0x3e953f7b,0xbf753e48,0x3f623f0e,0xbef13f55,
0xbef1bf6d,0x3f62bec4,0xbf75bec4,0x3e95bf6d,0x3f223f55,0xbf463f0e,0x3f7f3e48,0xbdc93f7b,0x3f80,0xbf800000,0x3f80,0xbf800000,
0xbf80,0x3f800000,0xbf80,0x3f800000,0x3f80,0xbf800000,0x3f80,0xbf800000,0xbf80,0x3f800000,0xbf80,0x3f800000,
0x3dc9bf80,0x3f7f0000,0x3f46bf35,0x3f223f35,0xbe953f7b,0xbf75be48,0xbf623f0e,0xbef1bf55,0x3ef1bf6d,0x3f623ec4,0x3f75bec4,0x3e953f6d,
0xbf223f55,0xbf46bf0e,0xbf7f3e48,0xbdc9bf7b,0xbe483f80,0xbf7b0000,0xbf7b0000,0x3e48bf80,0x3f0ebf6d,0x3f553ec4,0x3f553ec4,0xbf0e3f6d,
0xbf553f35,0xbf0ebf35,0xbf0ebf35,0x3f55bf35,0x3f7bbec4,0x3e483f6d,0x3e483f6d,0xbf7b3ec4,0x3e95bf80,0x3f750000,0x3ef13f35,0xbf623f35,
0xbf463f55,0xbf22bf0e,0x3dc9bf7b,0x3f7fbe48,0x3f7fbec4,0x3dc93f6d,0xbf223f6d,0xbf46bec4,0xbf62be48,0x3ef1bf7b,0x3f75bf0e,0x3e953f55,
0xbec43f80,0xbf6d0000,0x3ec4bf80,0x3f6d0000,0x3f6dbf35,0x3ec43f35,0xbf6d3f35,0xbec4bf35,0xbf6d0000,0x3ec4bf80,0x3f6d0000,0xbec43f80,
0x3ec43f35,0xbf6d3f35,0xbec4bf35,0x3f6dbf35,0x3ef1bf80,0x3f620000,0xbf753f35,0xbe95bf35,0xbf7f3f0e,0xbdc9bf55,0x3f463e48,0xbf223f7b,
0x3f223ec4,0xbf463f6d,0x3dc9bf6d,0x3f7fbec4,0x3e95bf7b,0x3f75be48,0xbf623f55,0xbef1bf0e,0xbf0e3f80,0xbf550000,0x3f550000,0xbf0e3f80,
0x3f7bbec4,0xbe483f6d,0x3e48bf6d,0x3f7bbec4,0xbe48bf35,0x3f7bbf35,0xbf7b3f35,0xbe48bf35,0xbf553f6d,0xbf0ebec4,0x3f0e3ec4,0xbf553f6d,
0x3f22bf80,0x3f460000,0xbdc9bf35,0x3f7fbf35,0xbf623e48,0x3ef1bf7b,0xbf753f55,0xbe95bf0e,0xbe953f6d,0xbf753ec4,0x3ef13ec4,0xbf623f6d,
0x3f7fbf0e,0xbdc93f55,0x3f46bf7b,0x3f223e48,0xbf353f80,0xbf350000,0xbf353f80,0xbf350000,0x3f350000,0xbf353f80,0x3f350000,0xbf353f80,
0x3f35bf80,0x3f350000,0x3f35bf80,0x3f350000,0xbf350000,0x3f35bf80,0xbf350000,0x3f35bf80,0x3f46bf80,0x3f220000,0x3f7fbf35,0xbdc93f35,
0xbef1be48,0x3f62bf7b,0x3e95bf55,0x3f75bf0e,0xbf753f6d,0xbe95bec4,0xbf623ec4,0x3ef1bf6d,0x3dc93f0e,0xbf7f3f55,0xbf223f7b,0xbf463e48,
0xbf553f80,0xbf0e0000,0xbf0e0000,0x3f55bf80,0x3e483ec4,0xbf7b3f6d,0xbf7b3f6d,0xbe48bec4,0x3f7bbf35,0xbe483f35,0xbe483f35,0xbf7b3f35,
0x3f0ebf6d,0x3f55bec4,0x3f55bec4,0xbf0e3f6d,0x3f62bf80,0x3ef10000,0xbe953f35,0xbf753f35,0x3dc9bf0e,0x3f7fbf55,0x3f22be48,0xbf463f7b,
0xbf463ec4,0x3f22bf6d,0x3f7fbf6d,0x3dc93ec4,0xbf753f7b,0xbe95be48,0x3ef1bf55,0x3f62bf0e,0xbf6d3f80,0xbec40000,0x3f6dbf80,0x3ec40000,
0xbec43f35,0xbf6d3f35,0x3ec4bf35,0x3f6dbf35,0x3ec40000,0xbf6d3f80,0xbec40000,0x3f6dbf80,0x3f6dbf35,0xbec43f35,0xbf6d3f35,0x3ec4bf35,
0x3f75bf80,0x3e950000,0xbf623f35,0x3ef1bf35,0x3f22bf55,0x3f46bf0e,0xbf7f3f7b,0xbdc9be48,0x3dc9bec4,0x3f7fbf6d,0xbf463f6d,0xbf223ec4,
0xbef13e48,0x3f62bf7b,0xbe953f0e,0xbf753f55,0xbf7b3f80,0xbe480000,0x3e480000,0xbf7b3f80,0xbf553f6d,0xbf0e3ec4,0x3f0ebec4,0xbf553f6d,
0xbf0e3f35,0xbf553f35,0x3f55bf35,0xbf0e3f35,0xbe483ec4,0xbf7b3f6d,0x3f7bbf6d,0xbe483ec4,0x3f7fbf80,0x3dc90000,0x3f22bf35,0x3f46bf35,
0x3f75bf7b,0x3e95be48,0x3ef1bf0e,0x3f62bf55,0x3f62bf6d,0x3ef1bec4,0x3e95bec4,0x3f75bf6d,0x3f46bf55,0x3f22bf0e,0x3dc9be48,0x3f7fbf7b,
0x3f803f80,0xbf803f80,0x3f803f80,0xbf803f80,0x3f803f80,0xbf803f80,0x3f803f80,0xbf803f80,0x3f803f80,0xbf803f80,0x3f803f80,0xbf803f80,
0x3f803f80,0xbf803f80,0x3f803f80,0xbf803f80,0x3dc90000,0x3f7f3f80,0x3f463f35,0x3f223f35,0x3e953e48,0x3f753f7b,0x3f623f55,0x3ef13f0e,
0x3ef13ec4,0x3f623f6d,0x3f753f6d,0x3e953ec4,0x3f223f0e,0x3f463f55,0x3f7f3f7b,0x3dc93e48,0xbf7bbf80,0x3e480000,0x3e480000,0x3f7b3f80,
0xbf55bf6d,0x3f0e3ec4,0x3f0e3ec4,0x3f553f6d,0xbf0ebf35,0x3f553f35,0x3f553f35,0x3f0e3f35,0xbe48bec4,0x3f7b3f6d,0x3f7b3f6d,0x3e483ec4,
0xbe950000,0xbf75bf80,0xbef1bf35,0x3f623f35,0xbf46bf0e,0xbf22bf55,0x3dc9be48,0x3f7f3f7b,0xbf7fbf6d,0xbdc9bec4,0x3f223ec4,0x3f463f6d,
0xbf62bf7b,0x3ef13e48,0x3f753f55,0x3e953f0e,0x3f6d3f80,0xbec40000,0xbf6dbf80,0x3ec40000,0x3ec43f35,0xbf6dbf35,0xbec4bf35,0x3f6d3f35,
0xbec40000,0xbf6dbf80,0x3ec40000,0x3f6d3f80,0xbf6dbf35,0xbec4bf35,0x3f6d3f35,0x3ec43f35,0x3ef10000,0x3f623f80,0xbf75bf35,0xbe95bf35,
0x3f7f3f55,0x3dc93f0e,0xbf46bf7b,0x3f223e48,0x3f223f6d,0xbf46bec4,0x3dc9bec4,0x3f7f3f6d,0xbe953e48,0xbf75bf7b,0x3f623f0e,0x3ef13f55,
0xbf55bf80,0x3f0e0000,0xbf0e0000,0xbf55bf80,0x3e48bec4,0x3f7b3f6d,0xbf7bbf6d,0x3e48bec4,0x3f7b3f35,0x3e483f35,0xbe48bf35,0x3f7b3f35,
0x3f0e3f6d,0xbf55bec4,0x3f553ec4,0x3f0e3f6d,0xbf220000,0xbf46bf80,0x3dc93f35,0xbf7fbf35,0xbf62bf7b,0x3ef1be48,0xbf75bf0e,0xbe95bf55,
0x3e95bec4,0x3f753f6d,0xbef1bf6d,0x3f623ec4,0x3f7f3f55,0xbdc93f0e,0x3f463e48,0x3f223f7b,0x3f353f80,0xbf350000,0x3f353f80,0xbf350000,
0xbf350000,0xbf35bf80,0xbf350000,0xbf35bf80,0xbf35bf80,0x3f350000,0xbf35bf80,0x3f350000,0x3f350000,0x3f353f80,0x3f350000,0x3f353f80,
0x3f460000,0x3f223f80,0x3f7f3f35,0xbdc93f35,0x3ef13f7b,0xbf62be48,0xbe953f0e,0xbf75bf55,0xbf75bec4,0xbe95bf6d,0xbf62bf6d,0x3ef1bec4,
0xbdc9bf55,0x3f7f3f0e,0x3f22be48,0x3f463f7b,0xbf0ebf80,0x3f550000,0x3f550000,0x3f0e3f80,0x3f7b3ec4,0x3e483f6d,0x3e483f6d,0xbf7bbec4,
0xbe483f35,0xbf7bbf35,0xbf7bbf35,0x3e48bf35,0xbf55bf6d,0x3f0ebec4,0x3f0ebec4,0x3f553f6d,0xbf620000,0xbef1bf80,0x3e95bf35,0x3f753f35,
0x3dc9bf55,0x3f7f3f0e,0x3f223f7b,0xbf463e48,0x3f463f6d,0xbf223ec4,0xbf7fbec4,0xbdc9bf6d,0xbf75be48,0xbe95bf7b,0x3ef1bf0e,0x3f623f55,
0x3ec43f80,0xbf6d0000,0xbec4bf80,0x3f6d0000,0xbf6dbf35,0x3ec4bf35,0x3f6d3f35,0xbec43f35,0x3f6d0000,0x3ec43f80,0xbf6d0000,0xbec4bf80,
0xbec43f35,0xbf6dbf35,0x3ec4bf35,0x3f6d3f35,0x3f750000,0x3e953f80,0xbf62bf35,0x3ef1bf35,0xbf223f0e,0xbf46bf55,0x3f7f3e48,0x3dc93f7b,
0x3dc9bf6d,0x3f7f3ec4,0xbf463ec4,0xbf22bf6d,0x3ef13f7b,0xbf623e48,0x3e95bf55,0x3f753f0e,0xbe48bf80,0x3f7b0000,0xbf7b0000,0xbe48bf80,
0x3f0e3f6d,0xbf553ec4,0x3f55bec4,0x3f0e3f6d,0xbf55bf35,0x3f0ebf35,0xbf0e3f35,0xbf55bf35,0x3f7b3ec4,0xbe483f6d,0x3e48bf6d,0x3f7b3ec4,
0xbf7f0000,0xbdc9bf80,0xbf223f35,0xbf46bf35,0x3f75be48,0x3e953f7b,0x3ef1bf55,0x3f623f0e,0xbf623ec4,0xbef1bf6d,0xbe953f6d,0xbf75bec4,
0x3f46bf0e,0x3f223f55,0x3dc9bf7b,0x3f7f3e48,0x3f80,0xbf800000,0x3f80,0xbf800000,0xbf80,0x3f800000,0xbf80,0x3f800000,
0x3f80,0xbf800000,0x3f80,0xbf800000,0xbf80,0x3f800000,0xbf80,0x3f800000,0x3f7f0000,0xbdc93f80,0x3f223f35,0xbf463f35,
0xbf75be48,0x3e95bf7b,0xbef1bf55,0x3f62bf0e,0x3f623ec4,0xbef13f6d,0x3e953f6d,0xbf753ec4,0xbf46bf0e,0x3f22bf55,0xbdc9bf7b,0x3f7fbe48,
0x3e48bf80,0x3f7b0000,0x3f7b0000,0xbe483f80,0xbf0e3f6d,0xbf55bec4,0xbf55bec4,0x3f0ebf6d,0x3f55bf35,0x3f0e3f35,0x3f0e3f35,0xbf553f35,
0xbf7b3ec4,0xbe48bf6d,0xbe48bf6d,0x3f7bbec4,0xbf750000,0x3e95bf80,0x3f62bf35,0x3ef13f35,0x3f223f0e,0xbf463f55,0xbf7f3e48,0x3dc9bf7b,
0xbdc9bf6d,0x3f7fbec4,0x3f463ec4,0xbf223f6d,0xbef13f7b,0xbf62be48,0xbe95bf55,0x3f75bf0e,0xbec43f80,0xbf6d0000,0x3ec4bf80,0x3f6d0000,
0x3f6dbf35,0x3ec43f35,0xbf6d3f35,0xbec4bf35,0xbf6d0000,0x3ec4bf80,0x3f6d0000,0xbec43f80,0x3ec43f35,0xbf6d3f35,0xbec4bf35,0x3f6dbf35,
0x3f620000,0xbef13f80,0xbe95bf35,0x3f75bf35,0xbdc9bf55,0x3f7fbf0e,0xbf223f7b,0xbf46be48,0xbf463f6d,0xbf22bec4,0x3f7fbec4,0xbdc93f6d,
0x3f75be48,0xbe953f7b,0xbef1bf0e,0x3f62bf55,0x3f0ebf80,0x3f550000,0xbf550000,0x3f0ebf80,0xbf7b3ec4,0x3e48bf6d,0xbe483f6d,0xbf7b3ec4,
0x3e483f35,0xbf7b3f35,0x3f7bbf35,0x3e483f35,0x3f55bf6d,0x3f0e3ec4,0xbf0ebec4,0x3f55bf6d,0xbf460000,0x3f22bf80,0xbf7f3f35,0xbdc9bf35,
0xbef13f7b,0xbf623e48,0x3e953f0e,0xbf753f55,0x3f75bec4,0xbe953f6d,0x3f62bf6d,0x3ef13ec4,0x3dc9bf55,0x3f7fbf0e,0xbf22be48,0x3f46bf7b,
0xbf353f80,0xbf350000,0xbf353f80,0xbf350000,0x3f350000,0xbf353f80,0x3f350000,0xbf353f80,0x3f35bf80,0x3f350000,0x3f35bf80,0x3f350000,
0xbf350000,0x3f35bf80,0xbf350000,0x3f35bf80,0x3f220000,0xbf463f80,0xbdc93f35,0xbf7f3f35,0x3f62bf7b,0x3ef13e48,0x3f75bf0e,0xbe953f55,
0xbe95bec4,0x3f75bf6d,0x3ef1bf6d,0x3f62bec4,0xbf7f3f55,0xbdc9bf0e,0xbf463e48,0x3f22bf7b,0x3f55bf80,0x3f0e0000,0x3f0e0000,0xbf553f80,
0xbe48bec4,0x3f7bbf6d,0x3f7bbf6d,0x3e483ec4,0xbf7b3f35,0x3e48bf35,0x3e48bf35,0x3f7bbf35,0xbf0e3f6d,0xbf553ec4,0xbf553ec4,0x3f0ebf6d,
0xbef10000,0x3f62bf80,0x3f75bf35,0xbe953f35,0xbf7f3f55,0x3dc9bf0e,0x3f46bf7b,0x3f22be48,0xbf223f6d,0xbf463ec4,0xbdc9bec4,0x3f7fbf6d,
0x3e953e48,0xbf753f7b,0xbf623f0e,0x3ef1bf55,0xbf6d3f80,0xbec40000,0x3f6dbf80,0x3ec40000,0xbec43f35,0xbf6d3f35,0x3ec4bf35,0x3f6dbf35,
0x3ec40000,0xbf6d3f80,0xbec40000,0x3f6dbf80,0x3f6dbf35,0xbec43f35,0xbf6d3f35,0x3ec4bf35,0x3e950000,0xbf753f80,0x3ef1bf35,0x3f62bf35,
0x3f46bf0e,0xbf223f55,0xbdc9be48,0x3f7fbf7b,0x3f7fbf6d,0xbdc93ec4,0xbf223ec4,0x3f46bf6d,0x3f62bf7b,0x3ef1be48,0xbf753f55,0x3e95bf0e,
0x3f7bbf80,0x3e480000,0xbe480000,0x3f7bbf80,0x3f55bf6d,0x3f0ebec4,0xbf0e3ec4,0x3f55bf6d,0x3f0ebf35,0x3f55bf35,0xbf553f35,0x3f0ebf35,
0x3e48bec4,0x3f7bbf6d,0xbf7b3f6d,0x3e48bec4,0xbdc90000,0x3f7fbf80,0xbf463f35,0x3f22bf35,0xbe953e48,0x3f75bf7b,0xbf623f55,0x3ef1bf0e,
0xbef13ec4,0x3f62bf6d,0xbf753f6d,0x3e95bec4,0xbf223f0e,0x3f46bf55,0xbf7f3f7b,0x3dc9be48,0x40003f80,0x3fb53f80,0x3f80,0xbfb53f80,
0x40004000,0xbfb50000,0x0,0xbfb5c000,0x40004000,0xbfb5c000,0x0,0x3fb50000,0x40004000,0x3fb50000,0x0,0x3fb54000,
0x3fff3f80,0x3fa23f80,0xbe49bf80,0xbfc6bf80,0x3ff53ffb,0xbfe2bec8,0xbf15bec8,0xbf71bffb,0x3fe23fed,0xbf15bfed,0xbf71bf44,0x3ff53f44,
0x3fc63fd5,0x3fff3f8e,0xbfa2bf8e,0x3e493fd5,0x3ffb3f80,0x3f8e3f80,0xbec83f80,0xbfd53f80,0x3fd53fed,0xbffbbf44,0xbf8ebf44,0xbec8bfed,
0x3f8e3fb5,0x3ec8bfb5,0xbfd5bfb5,0x3ffb3fb5,0x3ec83f44,0x3fd53fed,0xbffbbfed,0xbf8e3f44,0x3ff53f80,0x3f713f80,0xbf15bf80,0xbfe2bf80,
0x3fa23fd5,0xbfffbf8e,0xbfc6bf8e,0x3e49bfd5,0x3e493f44,0x3fa2bf44,0xbfffbfed,0x3fc63fed,0xbf71bec8,0x3f153ffb,0xbfe2bffb,0xbff5bec8,
0x3fed3f80,0x3f443f80,0xbf443f80,0xbfed3f80,0x3f443fb5,0xbfedbfb5,0xbfedbfb5,0x3f44bfb5,0xbf440000,0x3fed0000,0xbfedc000,0x3f444000,
0xbfedbfb5,0xbf443fb5,0xbf44bfb5,0xbfedbfb5,0x3fe23f80,0x3f153f80,0xbf71bf80,0xbff5bf80,0x3e493f8e,0xbfc6bfd5,0xbfffbfd5,0x3fa2bf8e,
0xbfc6bf44,0x3fff3f44,0xbfa2bfed,0xbe493fed,0xbff5bffb,0xbfe23ec8,0x3f15bec8,0xbf71bffb,0x3fd53f80,0x3ec83f80,0xbf8e3f80,0xbffb3f80,
0xbec83f44,0xbf8ebfed,0xbffbbfed,0x3fd5bf44,0xbffbbfb5,0x3fd53fb5,0xbec8bfb5,0xbf8e3fb5,0xbf8ebfed,0xbffbbf44,0x3fd53f44,0x3ec8bfed,
0x3fc63f80,0x3e493f80,0xbfa2bf80,0xbfffbf80,0xbf713ec8,0xbf15bffb,0xbfe2bffb,0x3ff5bec8,0xbff5bfed,0x3f713fed,0x3f15bf44,0xbfe23f44,
0x3e49bf8e,0xbfa2bfd5,0x3fff3fd5,0x3fc6bf8e,0x3f80,0xbfb53f80,0xc0003f80,0xbfb53f80,0xc000,0x3fb50000,0x40000000,0xbfb54000,
0x4000,0x3fb5c000,0xc0000000,0x3fb50000,0xc000,0xbfb50000,0x40000000,0x3fb5c000,0xbe493f80,0xbfc63f80,0xbfffbf80,0xbfa2bf80,
0x3f15bffb,0x3f713ec8,0x3ff53ec8,0xbfe23ffb,0xbf713fed,0x3ff5bfed,0xbfe2bf44,0x3f153f44,0x3fa2bfd5,0xbe49bf8e,0x3fc63f8e,0x3fffbfd5,
0xbec83f80,0xbfd53f80,0xbffb3f80,0xbf8e3f80,0x3f8ebfed,0x3ec83f44,0x3fd53f44,0xbffb3fed,0xbfd53fb5,0x3ffbbfb5,0xbf8ebfb5,0xbec83fb5,
0x3ffbbf44,0x3f8ebfed,0x3ec83fed,0x3fd5bf44,0xbf153f80,0xbfe23f80,0xbff5bf80,0xbf71bf80,0x3fc6bfd5,0xbe493f8e,0x3fa23f8e,0xbfff3fd5,
0xbfff3f44,0x3fc6bf44,0xbe49bfed,0xbfa23fed,0x3fe23ec8,0x3ff5bffb,0xbf713ffb,0x3f153ec8,0xbf443f80,0xbfed3f80,0xbfed3f80,0xbf443f80,
0x3fedbfb5,0xbf443fb5,0x3f443fb5,0xbfed3fb5,0xbfed0000,0x3f440000,0x3f44c000,0xbfed4000,0x3f443fb5,0x3fedbfb5,0xbfed3fb5,0xbf443fb5,
0xbf713f80,0xbff53f80,0xbfe2bf80,0xbf15bf80,0x3fffbf8e,0xbfa23fd5,0x3e493fd5,0xbfc63f8e,0xbfa2bf44,0xbe493f44,0x3fc6bfed,0xbfff3fed,
0xbf153ffb,0x3f71bec8,0xbff53ec8,0xbfe23ffb,0xbf8e3f80,0xbffb3f80,0xbfd53f80,0xbec83f80,0x3ffbbf44,0xbfd53fed,0xbec83fed,0xbf8e3f44,
0xbec8bfb5,0xbf8e3fb5,0x3ffbbfb5,0xbfd53fb5,0xbfd53fed,0xbec83f44,0xbf8ebf44,0xbffb3fed,0xbfa23f80,0xbfff3f80,0xbfc6bf80,0xbe49bf80,
0x3fe2bec8,0xbff53ffb,0xbf713ffb,0xbf153ec8,0x3f15bfed,0xbfe23fed,0x3ff5bf44,0xbf713f44,0xbfff3f8e,0xbfc63fd5,0x3e49bfd5,0xbfa23f8e,
0xc0003f80,0xbfb53f80,0x3f80,0x3fb53f80,0xc0004000,0x3fb50000,0x0,0x3fb5c000,0xc0004000,0x3fb5c000,0x0,0xbfb50000,
0xc0004000,0xbfb50000,0x0,0xbfb54000,0xbfff3f80,0xbfa23f80,0x3e49bf80,0x3fc6bf80,0xbff53ffb,0x3fe2bec8,0x3f15bec8,0x3f71bffb,
0xbfe23fed,0x3f15bfed,0x3f71bf44,0xbff53f44,0xbfc63fd5,0xbfff3f8e,0x3fa2bf8e,0xbe493fd5,0xbffb3f80,0xbf8e3f80,0x3ec83f80,0x3fd53f80,
0xbfd53fed,0x3ffbbf44,0x3f8ebf44,0x3ec8bfed,0xbf8e3fb5,0xbec8bfb5,0x3fd5bfb5,0xbffb3fb5,0xbec83f44,0xbfd53fed,0x3ffbbfed,0x3f8e3f44,
0xbff53f80,0xbf713f80,0x3f15bf80,0x3fe2bf80,0xbfa23fd5,0x3fffbf8e,0x3fc6bf8e,0xbe49bfd5,0xbe493f44,0xbfa2bf44,0x3fffbfed,0xbfc63fed,
0x3f71bec8,0xbf153ffb,0x3fe2bffb,0x3ff5bec8,0xbfed3f80,0xbf443f80,0x3f443f80,0x3fed3f80,0xbf443fb5,0x3fedbfb5,0x3fedbfb5,0xbf44bfb5,
0x3f440000,0xbfed0000,0x3fedc000,0xbf444000,0x3fedbfb5,0x3f443fb5,0x3f44bfb5,0x3fedbfb5,0xbfe23f80,0xbf153f80,0x3f71bf80,0x3ff5bf80,
0xbe493f8e,0x3fc6bfd5,0x3fffbfd5,0xbfa2bf8e,0x3fc6bf44,0xbfff3f44,0x3fa2bfed,0x3e493fed,0x3ff5bffb,0x3fe23ec8,0xbf15bec8,0x3f71bffb,
0xbfd53f80,0xbec83f80,0x3f8e3f80,0x3ffb3f80,0x3ec83f44,0x3f8ebfed,0x3ffbbfed,0xbfd5bf44,0x3ffbbfb5,0xbfd53fb5,0x3ec8bfb5,0x3f8e3fb5,
0x3f8ebfed,0x3ffbbf44,0xbfd53f44,0xbec8bfed,0xbfc63f80,0xbe493f80,0x3fa2bf80,0x3fffbf80,0x3f713ec8,0x3f15bffb,0x3fe2bffb,0xbff5bec8,
0x3ff5bfed,0xbf713fed,0xbf15bf44,0x3fe23f44,0xbe49bf8e,0x3fa2bfd5,0xbfff3fd5,0xbfc6bf8e,0x3f80,0x3fb53f80,0x40003f80,0x3fb53f80,
0xc000,0xbfb50000,0xc0000000,0x3fb54000,0x4000,0xbfb5c000,0x40000000,0xbfb50000,0xc000,0x3fb50000,0xc0000000,0xbfb5c000,
0x3e493f80,0x3fc63f80,0x3fffbf80,0x3fa2bf80,0xbf15bffb,0xbf713ec8,0xbff53ec8,0x3fe23ffb,0x3f713fed,0xbff5bfed,0x3fe2bf44,0xbf153f44,
0xbfa2bfd5,0x3e49bf8e,0xbfc63f8e,0xbfffbfd5,0x3ec83f80,0x3fd53f80,0x3ffb3f80,0x3f8e3f80,0xbf8ebfed,0xbec83f44,0xbfd53f44,0x3ffb3fed,
0x3fd53fb5,0xbffbbfb5,0x3f8ebfb5,0x3ec83fb5,0xbffbbf44,0xbf8ebfed,0xbec83fed,0xbfd5bf44,0x3f153f80,0x3fe23f80,0x3ff5bf80,0x3f71bf80,
0xbfc6bfd5,0x3e493f8e,0xbfa23f8e,0x3fff3fd5,0x3fff3f44,0xbfc6bf44,0x3e49bfed,0x3fa23fed,0xbfe23ec8,0xbff5bffb,0x3f713ffb,0xbf153ec8,
0x3f443f80,0x3fed3f80,0x3fed3f80,0x3f443f80,0xbfedbfb5,0x3f443fb5,0xbf443fb5,0x3fed3fb5,0x3fed0000,0xbf440000,0xbf44c000,0x3fed4000,
0xbf443fb5,0xbfedbfb5,0x3fed3fb5,0x3f443fb5,0x3f713f80,0x3ff53f80,0x3fe2bf80,0x3f15bf80,0xbfffbf8e,0x3fa23fd5,0xbe493fd5,0x3fc63f8e,
0x3fa2bf44,0x3e493f44,0xbfc6bfed,0x3fff3fed,0x3f153ffb,0xbf71bec8,0x3ff53ec8,0x3fe23ffb,0x3f8e3f80,0x3ffb3f80,0x3fd53f80,0x3ec83f80,
0xbffbbf44,0x3fd53fed,0x3ec83fed,0x3f8e3f44,0x3ec8bfb5,0x3f8e3fb5,0xbffbbfb5,0x3fd53fb5,0x3fd53fed,0x3ec83f44,0x3f8ebf44,0x3ffb3fed,
0x3fa23f80,0x3fff3f80,0x3fc6bf80,0x3e49bf80,0xbfe2bec8,0x3ff53ffb,0x3f713ffb,0x3f153ec8,0xbf15bfed,0x3fe23fed,0xbff5bf44,0x3f713f44,
0x3fff3f8e,0x3fc63fd5,0xbe49bfd5,0x3fa23f8e,0x40004000,0x3fb54000,0x0,0xbfb50000,0x40004000,0xbfb50000,0x0,0xbfb5c000,
0x40004000,0xbfb5c000,0x0,0x3fb50000,0x40004000,0x3fb50000,0x0,0x3fb54000,0x3fa23fb5,0xbe493fb5,0xbfc6bfb5,0xbfffbfb5,
0x3f713f8e,0xbff5bfd5,0xbfe2bfd5,0x3f15bf8e,0x3f153f44,0x3f71bf44,0xbff5bfed,0x3fe23fed,0x3e493ec8,0x3fc63ffb,0xbfffbffb,0xbfa23ec8,
0xbec80000,0xbfd50000,0xbffbc000,0xbf8ec000,0xbf8ebf44,0xbec8bfed,0xbfd5bfed,0x3ffb3f44,0xbfd5bfb5,0x3ffb3fb5,0xbf8ebfb5,0xbec83fb5,
0xbffbbfed,0xbf8e3f44,0xbec8bf44,0xbfd5bfed,0xbfe2bfb5,0xbff5bfb5,0xbf71bfb5,0x3f15bfb5,0xbfffbffb,0x3fc6bec8,0x3e49bec8,0x3fa23ffb,
0xbfc6bfed,0x3e493fed,0x3fa23f44,0xbfffbf44,0xbf15bf8e,0xbfe2bfd5,0x3ff53fd5,0x3f71bf8e,0xbfedc000,0xbf44c000,0x3f440000,0x3fed0000,
0xbf44bfb5,0x3fed3fb5,0x3fed3fb5,0xbf443fb5,0x3f440000,0xbfed0000,0x3fed4000,0xbf44c000,0x3fed3fb5,0x3f44bfb5,0x3f443fb5,0x3fed3fb5,
0xbf15bfb5,0x3f71bfb5,0x3ff53fb5,0x3fe23fb5,0x3fa23ec8,0x3e493ffb,0x3fc63ffb,0xbfffbec8,0x3fff3fed,0xbfa2bfed,0xbe493f44,0x3fc6bf44,
0x3f713fd5,0x3ff53f8e,0xbfe2bf8e,0xbf153fd5,0x3f8e0000,0x3ffb0000,0x3fd54000,0x3ec84000,0x3ffb3fed,0xbfd53f44,0xbec83f44,0xbf8ebfed,
0x3ec83fb5,0x3f8ebfb5,0xbffbbfb5,0x3fd53fb5,0xbfd5bf44,0xbec83fed,0xbf8ebfed,0xbffbbf44,0x3fff3fb5,0x3fc63fb5,0x3e493fb5,0xbfa23fb5,
0x3f153fd5,0xbfe2bf8e,0xbff5bf8e,0x3f71bfd5,0xbfe2bf44,0x3ff53f44,0xbf71bfed,0xbf153fed,0xbfa2bffb,0xbfffbec8,0x3fc63ec8,0x3e49bffb,
0x4000,0xbfb54000,0xc0000000,0xbfb50000,0xc000,0x3fb50000,0x40000000,0xbfb54000,0x4000,0x3fb5c000,0xc0000000,0x3fb50000,
0xc000,0xbfb50000,0x40000000,0x3fb5c000,0xbfc63fb5,0xbfff3fb5,0xbfa2bfb5,0x3e49bfb5,0x3fe2bf8e,0xbf153fd5,0x3f713fd5,0xbff53f8e,
0xbff53f44,0x3fe2bf44,0xbf15bfed,0xbf713fed,0x3fffbec8,0x3fa2bffb,0x3e493ffb,0x3fc6bec8,0xbffb0000,0xbf8e0000,0x3ec8c000,0x3fd5c000,
0x3fd53f44,0xbffb3fed,0xbf8e3fed,0xbec8bf44,0xbf8ebfb5,0xbec83fb5,0x3fd5bfb5,0xbffb3fb5,0x3ec83fed,0x3fd5bf44,0xbffb3f44,0xbf8e3fed,
0xbf71bfb5,0x3f15bfb5,0x3fe2bfb5,0x3ff5bfb5,0xbe493ffb,0xbfa23ec8,0xbfff3ec8,0x3fc6bffb,0x3fa2bfed,0xbfff3fed,0x3fc63f44,0xbe49bf44,
0xbff53f8e,0xbf713fd5,0xbf15bfd5,0xbfe23f8e,0x3f44c000,0x3fedc000,0x3fed0000,0x3f440000,0xbfed3fb5,0x3f44bfb5,0xbf44bfb5,0x3fedbfb5,
0x3fed0000,0xbf440000,0xbf444000,0x3fedc000,0xbf44bfb5,0xbfed3fb5,0x3fedbfb5,0x3f44bfb5,0x3ff5bfb5,0x3fe2bfb5,0x3f153fb5,0xbf713fb5,
0xbfc6bec8,0x3fffbffb,0x3fa2bffb,0x3e493ec8,0xbe493fed,0x3fc6bfed,0xbfff3f44,0x3fa2bf44,0x3fe2bfd5,0x3f15bf8e,0x3f713f8e,0x3ff5bfd5,
0x3fd50000,0x3ec80000,0xbf8e4000,0xbffb4000,0x3ec8bfed,0x3f8ebf44,0x3ffbbf44,0xbfd53fed,0xbffb3fb5,0x3fd5bfb5,0xbec8bfb5,0xbf8e3fb5,
0x3f8e3f44,0x3ffbbfed,0xbfd53fed,0xbec83f44,0x3e493fb5,0xbfa23fb5,0xbfff3fb5,0xbfc63fb5,0x3ff5bfd5,0xbf713f8e,0x3f153f8e,0xbfe23fd5,
0xbf71bf44,0xbf153f44,0x3fe2bfed,0xbff53fed,0xbfc63ffb,0xbe493ec8,0xbfa2bec8,0xbfff3ffb,0xc0004000,0xbfb54000,0x0,0x3fb50000,
0xc0004000,0x3fb50000,0x0,0x3fb5c000,0xc0004000,0x3fb5c000,0x0,0xbfb50000,0xc0004000,0xbfb50000,0x0,0xbfb54000,
0xbfa23fb5,0x3e493fb5,0x3fc6bfb5,0x3fffbfb5,0xbf713f8e,0x3ff5bfd5,0x3fe2bfd5,0xbf15bf8e,0xbf153f44,0xbf71bf44,0x3ff5bfed,0xbfe23fed,
0xbe493ec8,0xbfc63ffb,0x3fffbffb,0x3fa23ec8,0x3ec80000,0x3fd50000,0x3ffbc000,0x3f8ec000,0x3f8ebf44,0x3ec8bfed,0x3fd5bfed,0xbffb3f44,
0x3fd5bfb5,0xbffb3fb5,0x3f8ebfb5,0x3ec83fb5,0x3ffbbfed,0x3f8e3f44,0x3ec8bf44,0x3fd5bfed,0x3fe2bfb5,0x3ff5bfb5,0x3f71bfb5,0xbf15bfb5,
0x3fffbffb,0xbfc6bec8,0xbe49bec8,0xbfa23ffb,0x3fc6bfed,0xbe493fed,0xbfa23f44,0x3fffbf44,0x3f15bf8e,0x3fe2bfd5,0xbff53fd5,0xbf71bf8e,
0x3fedc000,0x3f44c000,0xbf440000,0xbfed0000,0x3f44bfb5,0xbfed3fb5,0xbfed3fb5,0x3f443fb5,0xbf440000,0x3fed0000,0xbfed4000,0x3f44c000,
0xbfed3fb5,0xbf44bfb5,0xbf443fb5,0xbfed3fb5,0x3f15bfb5,0xbf71bfb5,0xbff53fb5,0xbfe23fb5,0xbfa23ec8,0xbe493ffb,0xbfc63ffb,0x3fffbec8,
0xbfff3fed,0x3fa2bfed,0x3e493f44,0xbfc6bf44,0xbf713fd5,0xbff53f8e,0x3fe2bf8e,0x3f153fd5,0xbf8e0000,0xbffb0000,0xbfd54000,0xbec84000,
0xbffb3fed,0x3fd53f44,0x3ec83f44,0x3f8ebfed,0xbec83fb5,0xbf8ebfb5,0x3ffbbfb5,0xbfd53fb5,0x3fd5bf44,0x3ec83fed,0x3f8ebfed,0x3ffbbf44,
0xbfff3fb5,0xbfc63fb5,0xbe493fb5,0x3fa23fb5,0xbf153fd5,0x3fe2bf8e,0x3ff5bf8e,0xbf71bfd5,0x3fe2bf44,0xbff53f44,0x3f71bfed,0x3f153fed,
0x3fa2bffb,0x3fffbec8,0xbfc63ec8,0xbe49bffb,0x4000,0x3fb54000,0x40000000,0x3fb50000,0xc000,0xbfb50000,0xc0000000,0x3fb54000,
0x4000,0xbfb5c000,0x40000000,0xbfb50000,0xc000,0x3fb50000,0xc0000000,0xbfb5c000,0x3fc63fb5,0x3fff3fb5,0x3fa2bfb5,0xbe49bfb5,
0xbfe2bf8e,0x3f153fd5,0xbf713fd5,0x3ff53f8e,0x3ff53f44,0xbfe2bf44,0x3f15bfed,0x3f713fed,0xbfffbec8,0xbfa2bffb,0xbe493ffb,0xbfc6bec8,
0x3ffb0000,0x3f8e0000,0xbec8c000,0xbfd5c000,0xbfd53f44,0x3ffb3fed,0x3f8e3fed,0x3ec8bf44,0x3f8ebfb5,0x3ec83fb5,0xbfd5bfb5,0x3ffb3fb5,
0xbec83fed,0xbfd5bf44,0x3ffb3f44,0x3f8e3fed,0x3f71bfb5,0xbf15bfb5,0xbfe2bfb5,0xbff5bfb5,0x3e493ffb,0x3fa23ec8,0x3fff3ec8,0xbfc6bffb,
0xbfa2bfed,0x3fff3fed,0xbfc63f44,0x3e49bf44,0x3ff53f8e,0x3f713fd5,0x3f15bfd5,0x3fe23f8e,0xbf44c000,0xbfedc000,0xbfed0000,0xbf440000,
0x3fed3fb5,0xbf44bfb5,0x3f44bfb5,0xbfedbfb5,0xbfed0000,0x3f440000,0x3f444000,0xbfedc000,0x3f44bfb5,0x3fed3fb5,0xbfedbfb5,0xbf44bfb5,
0xbff5bfb5,0xbfe2bfb5,0xbf153fb5,0x3f713fb5,0x3fc6bec8,0xbfffbffb,0xbfa2bffb,0xbe493ec8,0x3e493fed,0xbfc6bfed,0x3fff3f44,0xbfa2bf44,
0xbfe2bfd5,0xbf15bf8e,0xbf713f8e,0xbff5bfd5,0xbfd50000,0xbec80000,0x3f8e4000,0x3ffb4000,0xbec8bfed,0xbf8ebf44,0xbffbbf44,0x3fd53fed,
0x3ffb3fb5,0xbfd5bfb5,0x3ec8bfb5,0x3f8e3fb5,0xbf8e3f44,0xbffbbfed,0x3fd53fed,0x3ec83f44,0xbe493fb5,0x3fa23fb5,0x3fff3fb5,0x3fc63fb5,
0xbff5bfd5,0x3f713f8e,0xbf153f8e,0x3fe23fd5,0x3f71bf44,0x3f153f44,0xbfe2bfed,0x3ff53fed,0x3fc63ffb,0x3e493ec8,0x3fa2bec8,0x3fff3ffb,
0x40004000,0x3fb54000,0x0,0xbfb50000,0x40004000,0xbfb50000,0x0,0xbfb5c000,0x40004000,0xbfb5c000,0x0,0x3fb50000,
0x40004000,0x3fb50000,0x0,0x3fb54000,0xbe490000,0xbfc60000,0xbfffc000,0xbfa2c000,0xbf15bec8,0xbf71bffb,0xbff5bffb,0x3fe23ec8,
0xbf71bf44,0x3ff53f44,0xbfe2bfed,0x3f153fed,0xbfa2bf8e,0x3e493fd5,0xbfc6bfd5,0xbfffbf8e,0xbffbc000,0xbf8ec000,0x3ec80000,0x3fd50000,
0xbfd5bfed,0x3ffb3f44,0x3f8e3f44,0x3ec83fed,0xbf8ebfb5,0xbec83fb5,0x3fd53fb5,0xbffbbfb5,0xbec8bf44,0xbfd5bfed,0x3ffb3fed,0x3f8ebf44,
0x3f150000,0x3fe20000,0x3ff54000,0x3f714000,0x3fc63f8e,0xbe493fd5,0x3fa23fd5,0xbfffbf8e,0x3fff3fed,0xbfc6bfed,0x3e493f44,0x3fa2bf44,
0x3fe23ffb,0x3ff53ec8,0xbf71bec8,0x3f153ffb,0x3fed4000,0x3f444000,0xbf440000,0xbfed0000,0x3f443fb5,0xbfedbfb5,0xbfedbfb5,0x3f44bfb5,
0xbf440000,0x3fed0000,0xbfedc000,0x3f444000,0xbfedbfb5,0xbf443fb5,0xbf44bfb5,0xbfedbfb5,0xbf710000,0xbff50000,0xbfe2c000,0xbf15c000,
0xbfffbfd5,0x3fa2bf8e,0xbe49bf8e,0x3fc63fd5,0xbfa2bfed,0xbe493fed,0x3fc63f44,0xbfffbf44,0x3f15bec8,0xbf71bffb,0x3ff53ffb,0x3fe2bec8,
0xbfd5c000,0xbec8c000,0x3f8e0000,0x3ffb0000,0x3ec8bf44,0x3f8e3fed,0x3ffb3fed,0xbfd53f44,0x3ffb3fb5,0xbfd5bfb5,0x3ec83fb5,0x3f8ebfb5,
0x3f8e3fed,0x3ffb3f44,0xbfd5bf44,0xbec83fed,0x3fa20000,0x3fff0000,0x3fc64000,0x3e494000,0x3fe23ffb,0xbff53ec8,0xbf713ec8,0xbf15bffb,
0xbf153f44,0x3fe2bf44,0xbff5bfed,0x3f713fed,0xbfffbfd5,0xbfc63f8e,0x3e49bf8e,0xbfa2bfd5,0x4000,0xbfb54000,0xc0000000,0xbfb50000,
0xc000,0x3fb50000,0x40000000,0xbfb54000,0x4000,0x3fb5c000,0xc0000000,0x3fb50000,0xc000,0xbfb50000,0x40000000,0x3fb5c000,
0xbfff0000,0xbfa20000,0x3e49c000,0x3fc6c000,0x3ff53ec8,0xbfe23ffb,0xbf153ffb,0xbf71bec8,0xbfe2bf44,0x3f153f44,0x3f71bfed,0xbff53fed,
0x3fc63f8e,0x3fffbfd5,0xbfa23fd5,0x3e493f8e,0x3ec8c000,0x3fd5c000,0x3ffb0000,0x3f8e0000,0xbf8e3fed,0xbec8bf44,0xbfd5bf44,0x3ffbbfed,
0x3fd5bfb5,0xbffb3fb5,0x3f8e3fb5,0x3ec8bfb5,0xbffb3f44,0xbf8e3fed,0xbec8bfed,0xbfd53f44,0x3ff50000,0x3f710000,0xbf154000,0xbfe24000,
0xbfa2bf8e,0x3fffbfd5,0x3fc6bfd5,0xbe493f8e,0x3e493fed,0x3fa2bfed,0xbfff3f44,0x3fc6bf44,0x3f71bffb,0xbf15bec8,0x3fe23ec8,0x3ff5bffb,
0xbf444000,0xbfed4000,0xbfed0000,0xbf440000,0x3fedbfb5,0xbf443fb5,0x3f443fb5,0xbfed3fb5,0xbfed0000,0x3f440000,0x3f44c000,0xbfed4000,
0x3f443fb5,0x3fedbfb5,0xbfed3fb5,0xbf443fb5,0xbfe20000,0xbf150000,0x3f71c000,0x3ff5c000,0x3e493fd5,0xbfc63f8e,0xbfff3f8e,0x3fa2bfd5,
0x3fc6bfed,0xbfff3fed,0x3fa23f44,0x3e49bf44,0xbff53ec8,0xbfe23ffb,0x3f15bffb,0xbf713ec8,0x3f8ec000,0x3ffbc000,0x3fd50000,0x3ec80000,
0xbffb3f44,0x3fd5bfed,0x3ec8bfed,0x3f8ebf44,0x3ec83fb5,0x3f8ebfb5,0xbffb3fb5,0x3fd5bfb5,0x3fd5bfed,0x3ec8bf44,0x3f8e3f44,0x3ffbbfed,
0x3fc60000,0x3e490000,0xbfa24000,0xbfff4000,0x3f71bffb,0x3f15bec8,0x3fe2bec8,0xbff53ffb,0xbff53f44,0x3f71bf44,0x3f15bfed,0xbfe23fed,
0xbe493fd5,0x3fa2bf8e,0xbfff3f8e,0xbfc63fd5,0xc0004000,0xbfb54000,0x0,0x3fb50000,0xc0004000,0x3fb50000,0x0,0x3fb5c000,
0xc0004000,0x3fb5c000,0x0,0xbfb50000,0xc0004000,0xbfb50000,0x0,0xbfb54000,0x3e490000,0x3fc60000,0x3fffc000,0x3fa2c000,
0x3f15bec8,0x3f71bffb,0x3ff5bffb,0xbfe23ec8,0x3f71bf44,0xbff53f44,0x3fe2bfed,0xbf153fed,0x3fa2bf8e,0xbe493fd5,0x3fc6bfd5,0x3fffbf8e,
0x3ffbc000,0x3f8ec000,0xbec80000,0xbfd50000,0x3fd5bfed,0xbffb3f44,0xbf8e3f44,0xbec83fed,0x3f8ebfb5,0x3ec83fb5,0xbfd53fb5,0x3ffbbfb5,
0x3ec8bf44,0x3fd5bfed,0xbffb3fed,0xbf8ebf44,0xbf150000,0xbfe20000,0xbff54000,0xbf714000,0xbfc63f8e,0x3e493fd5,0xbfa23fd5,0x3fffbf8e,
0xbfff3fed,0x3fc6bfed,0xbe493f44,0xbfa2bf44,0xbfe23ffb,0xbff53ec8,0x3f71bec8,0xbf153ffb,0xbfed4000,0xbf444000,0x3f440000,0x3fed0000,
0xbf443fb5,0x3fedbfb5,0x3fedbfb5,0xbf44bfb5,0x3f440000,0xbfed0000,0x3fedc000,0xbf444000,0x3fedbfb5,0x3f443fb5,0x3f44bfb5,0x3fedbfb5,
0x3f710000,0x3ff50000,0x3fe2c000,0x3f15c000,0x3fffbfd5,0xbfa2bf8e,0x3e49bf8e,0xbfc63fd5,0x3fa2bfed,0x3e493fed,0xbfc63f44,0x3fffbf44,
0xbf15bec8,0x3f71bffb,0xbff53ffb,0xbfe2bec8,0x3fd5c000,0x3ec8c000,0xbf8e0000,0xbffb0000,0xbec8bf44,0xbf8e3fed,0xbffb3fed,0x3fd53f44,
0xbffb3fb5,0x3fd5bfb5,0xbec83fb5,0xbf8ebfb5,0xbf8e3fed,0xbffb3f44,0x3fd5bf44,0x3ec83fed,0xbfa20000,0xbfff0000,0xbfc64000,0xbe494000,
0xbfe23ffb,0x3ff53ec8,0x3f713ec8,0x3f15bffb,0x3f153f44,0xbfe2bf44,0x3ff5bfed,0xbf713fed,0x3fffbfd5,0x3fc63f8e,0xbe49bf8e,0x3fa2bfd5,
0x4000,0x3fb54000,0x40000000,0x3fb50000,0xc000,0xbfb50000,0xc0000000,0x3fb54000,0x4000,0xbfb5c000,0x40000000,0xbfb50000,
0xc000,0x3fb50000,0xc0000000,0xbfb5c000,0x3fff0000,0x3fa20000,0xbe49c000,0xbfc6c000,0xbff53ec8,0x3fe23ffb,0x3f153ffb,0x3f71bec8,
0x3fe2bf44,0xbf153f44,0xbf71bfed,0x3ff53fed,0xbfc63f8e,0xbfffbfd5,0x3fa23fd5,0xbe493f8e,0xbec8c000,0xbfd5c000,0xbffb0000,0xbf8e0000,
0x3f8e3fed,0x3ec8bf44,0x3fd5bf44,0xbffbbfed,0xbfd5bfb5,0x3ffb3fb5,0xbf8e3fb5,0xbec8bfb5,0x3ffb3f44,0x3f8e3fed,0x3ec8bfed,0x3fd53f44,
0xbff50000,0xbf710000,0x3f154000,0x3fe24000,0x3fa2bf8e,0xbfffbfd5,0xbfc6bfd5,0x3e493f8e,0xbe493fed,0xbfa2bfed,0x3fff3f44,0xbfc6bf44,
0xbf71bffb,0x3f15bec8,0xbfe23ec8,0xbff5bffb,0x3f444000,0x3fed4000,0x3fed0000,0x3f440000,0xbfedbfb5,0x3f443fb5,0xbf443fb5,0x3fed3fb5,
0x3fed0000,0xbf440000,0xbf44c000,0x3fed4000,0xbf443fb5,0xbfedbfb5,0x3fed3fb5,0x3f443fb5,0x3fe20000,0x3f150000,0xbf71c000,0xbff5c000,
0xbe493fd5,0x3fc63f8e,0x3fff3f8e,0xbfa2bfd5,0xbfc6bfed,0x3fff3fed,0xbfa23f44,0xbe49bf44,0x3ff53ec8,0x3fe23ffb,0xbf15bffb,0x3f713ec8,
0xbf8ec000,0xbffbc000,0xbfd50000,0xbec80000,0x3ffb3f44,0xbfd5bfed,0xbec8bfed,0xbf8ebf44,0xbec83fb5,0xbf8ebfb5,0x3ffb3fb5,0xbfd5bfb5,
0xbfd5bfed,0xbec8bf44,0xbf8e3f44,0xbffbbfed,0xbfc60000,0xbe490000,0x3fa24000,0x3fff4000,0xbf71bffb,0xbf15bec8,0xbfe2bec8,0x3ff53ffb,
0x3ff53f44,0xbf71bf44,0xbf15bfed,0x3fe23fed,0x3e493fd5,0xbfa2bf8e,0x3fff3f8e,0x3fc63fd5,0x40004000,0x3fb54000,0x0,0xbfb50000,
0x40004000,0xbfb50000,0x0,0xbfb5c000,0x40004000,0xbfb5c000,0x0,0x3fb50000,0x40004000,0x3fb50000,0x0,0x3fb54000,
0xbfc6bfb5,0xbfffbfb5,0xbfa2bfb5,0x3e49bfb5,0xbfe2bfd5,0x3f15bf8e,0xbf71bf8e,0x3ff53fd5,0xbff5bfed,0x3fe23fed,0xbf15bf44,0xbf713f44,
0xbfffbffb,0xbfa23ec8,0xbe49bec8,0xbfc6bffb,0x3ec80000,0x3fd50000,0x3ffb4000,0x3f8e4000,0x3f8e3f44,0x3ec83fed,0x3fd53fed,0xbffbbf44,
0x3fd53fb5,0xbffbbfb5,0x3f8e3fb5,0x3ec8bfb5,0x3ffb3fed,0x3f8ebf44,0x3ec83f44,0x3fd53fed,0x3f713fb5,0xbf153fb5,0xbfe2bfb5,0xbff5bfb5,
0xbe493ec8,0xbfa2bffb,0xbfffbffb,0x3fc6bec8,0xbfa2bf44,0x3fff3f44,0xbfc6bfed,0x3e493fed,0xbff5bfd5,0xbf713f8e,0xbf15bf8e,0xbfe2bfd5,
0xbfedc000,0xbf44c000,0x3f440000,0x3fed0000,0xbf44bfb5,0x3fed3fb5,0x3fed3fb5,0xbf443fb5,0x3f440000,0xbfed0000,0x3fed4000,0xbf44c000,
0x3fed3fb5,0x3f44bfb5,0x3f443fb5,0x3fed3fb5,0x3ff53fb5,0x3fe23fb5,0x3f153fb5,0xbf713fb5,0x3fc63ffb,0xbfffbec8,0xbfa2bec8,0xbe49bffb,
0xbe493f44,0x3fc6bf44,0xbfffbfed,0x3fa23fed,0xbfe2bf8e,0xbf153fd5,0xbf71bfd5,0xbff5bf8e,0xbf8e0000,0xbffb0000,0xbfd5c000,0xbec8c000,
0xbffbbfed,0x3fd5bf44,0x3ec8bf44,0x3f8e3fed,0xbec8bfb5,0xbf8e3fb5,0x3ffb3fb5,0xbfd5bfb5,0x3fd53f44,0x3ec8bfed,0x3f8e3fed,0x3ffb3f44,
0xbe49bfb5,0x3fa2bfb5,0x3fff3fb5,0x3fc63fb5,0x3ff53f8e,0xbf713fd5,0x3f153fd5,0xbfe2bf8e,0x3f713fed,0x3f15bfed,0xbfe2bf44,0x3ff53f44,
0xbfc6bec8,0xbe493ffb,0xbfa2bffb,0xbfffbec8,0x4000,0xbfb54000,0xc0000000,0xbfb50000,0xc000,0x3fb50000,0x40000000,0xbfb54000,
0x4000,0x3fb5c000,0xc0000000,0x3fb50000,0xc000,0xbfb50000,0x40000000,0x3fb5c000,0xbfa2bfb5,0x3e49bfb5,0x3fc6bfb5,0x3fffbfb5,
0x3f713fd5,0xbff53f8e,0xbfe23f8e,0x3f15bfd5,0xbf15bfed,0xbf713fed,0x3ff5bf44,0xbfe23f44,0x3e493ffb,0x3fc6bec8,0xbfff3ec8,0xbfa23ffb,
0x3ffb0000,0x3f8e0000,0xbec84000,0xbfd54000,0xbfd5bf44,0x3ffbbfed,0x3f8ebfed,0x3ec83f44,0x3f8e3fb5,0x3ec8bfb5,0xbfd53fb5,0x3ffbbfb5,
0xbec8bfed,0xbfd53f44,0x3ffbbf44,0x3f8ebfed,0xbfe23fb5,0xbff53fb5,0xbf71bfb5,0x3f15bfb5,0x3fffbec8,0xbfc63ffb,0xbe493ffb,0xbfa23ec8,
0xbfc6bf44,0x3e493f44,0x3fa2bfed,0xbfff3fed,0x3f153fd5,0x3fe2bf8e,0xbff53f8e,0xbf713fd5,0x3f44c000,0x3fedc000,0x3fed0000,0x3f440000,
0xbfed3fb5,0x3f44bfb5,0xbf44bfb5,0x3fedbfb5,0x3fed0000,0xbf440000,0xbf444000,0x3fedc000,0xbf44bfb5,0xbfed3fb5,0x3fedbfb5,0x3f44bfb5,
0x3f153fb5,0xbf713fb5,0xbff53fb5,0xbfe23fb5,0x3fa2bffb,0x3e493ec8,0x3fc63ec8,0xbfff3ffb,0xbfff3f44,0x3fa2bf44,0x3e49bfed,0xbfc63fed,
0x3f713f8e,0x3ff5bfd5,0xbfe23fd5,0xbf153f8e,0xbfd50000,0xbec80000,0x3f8ec000,0x3ffbc000,0xbec83fed,0xbf8e3f44,0xbffb3f44,0x3fd5bfed,
0x3ffbbfb5,0xbfd53fb5,0x3ec83fb5,0x3f8ebfb5,0xbf8ebf44,0xbffb3fed,0x3fd5bfed,0x3ec8bf44,0x3fffbfb5,0x3fc6bfb5,0x3e493fb5,0xbfa23fb5,
0xbf15bf8e,0x3fe2bfd5,0x3ff5bfd5,0xbf713f8e,0xbfe23fed,0x3ff5bfed,0xbf71bf44,0xbf153f44,0x3fa23ec8,0x3fffbffb,0xbfc63ffb,0xbe493ec8,
0xc0004000,0xbfb54000,0x0,0x3fb50000,0xc0004000,0x3fb50000,0x0,0x3fb5c000,0xc0004000,0x3fb5c000,0x0,0xbfb50000,
0xc0004000,0xbfb50000,0x0,0xbfb54000,0x3fc6bfb5,0x3fffbfb5,0x3fa2bfb5,0xbe49bfb5,0x3fe2bfd5,0xbf15bf8e,0x3f71bf8e,0xbff53fd5,
0x3ff5bfed,0xbfe23fed,0x3f15bf44,0x3f713f44,0x3fffbffb,0x3fa23ec8,0x3e49bec8,0x3fc6bffb,0xbec80000,0xbfd50000,0xbffb4000,0xbf8e4000,
0xbf8e3f44,0xbec83fed,0xbfd53fed,0x3ffbbf44,0xbfd53fb5,0x3ffbbfb5,0xbf8e3fb5,0xbec8bfb5,0xbffb3fed,0xbf8ebf44,0xbec83f44,0xbfd53fed,
0xbf713fb5,0x3f153fb5,0x3fe2bfb5,0x3ff5bfb5,0x3e493ec8,0x3fa2bffb,0x3fffbffb,0xbfc6bec8,0x3fa2bf44,0xbfff3f44,0x3fc6bfed,0xbe493fed,
0x3ff5bfd5,0x3f713f8e,0x3f15bf8e,0x3fe2bfd5,0x3fedc000,0x3f44c000,0xbf440000,0xbfed0000,0x3f44bfb5,0xbfed3fb5,0xbfed3fb5,0x3f443fb5,
0xbf440000,0x3fed0000,0xbfed4000,0x3f44c000,0xbfed3fb5,0xbf44bfb5,0xbf443fb5,0xbfed3fb5,0xbff53fb5,0xbfe23fb5,0xbf153fb5,0x3f713fb5,
0xbfc63ffb,0x3fffbec8,0x3fa2bec8,0x3e49bffb,0x3e493f44,0xbfc6bf44,0x3fffbfed,0xbfa23fed,0x3fe2bf8e,0x3f153fd5,0x3f71bfd5,0x3ff5bf8e,
0x3f8e0000,0x3ffb0000,0x3fd5c000,0x3ec8c000,0x3ffbbfed,0xbfd5bf44,0xbec8bf44,0xbf8e3fed,0x3ec8bfb5,0x3f8e3fb5,0xbffb3fb5,0x3fd5bfb5,
0xbfd53f44,0xbec8bfed,0xbf8e3fed,0xbffb3f44,0x3e49bfb5,0xbfa2bfb5,0xbfff3fb5,0xbfc63fb5,0xbff53f8e,0x3f713fd5,0xbf153fd5,0x3fe2bf8e,
0xbf713fed,0xbf15bfed,0x3fe2bf44,0xbff53f44,0x3fc6bec8,0x3e493ffb,0x3fa2bffb,0x3fffbec8,0x4000,0x3fb54000,0x40000000,0x3fb50000,
0xc000,0xbfb50000,0xc0000000,0x3fb54000,0x4000,0xbfb5c000,0x40000000,0xbfb50000,0xc000,0x3fb50000,0xc0000000,0xbfb5c000,
0x3fa2bfb5,0xbe49bfb5,0xbfc6bfb5,0xbfffbfb5,0xbf713fd5,0x3ff53f8e,0x3fe23f8e,0xbf15bfd5,0x3f15bfed,0x3f713fed,0xbff5bf44,0x3fe23f44,
0xbe493ffb,0xbfc6bec8,0x3fff3ec8,0x3fa23ffb,0xbffb0000,0xbf8e0000,0x3ec84000,0x3fd54000,0x3fd5bf44,0xbffbbfed,0xbf8ebfed,0xbec83f44,
0xbf8e3fb5,0xbec8bfb5,0x3fd53fb5,0xbffbbfb5,0x3ec8bfed,0x3fd53f44,0xbffbbf44,0xbf8ebfed,0x3fe23fb5,0x3ff53fb5,0x3f71bfb5,0xbf15bfb5,
0xbfffbec8,0x3fc63ffb,0x3e493ffb,0x3fa23ec8,0x3fc6bf44,0xbe493f44,0xbfa2bfed,0x3fff3fed,0xbf153fd5,0xbfe2bf8e,0x3ff53f8e,0x3f713fd5,
0xbf44c000,0xbfedc000,0xbfed0000,0xbf440000,0x3fed3fb5,0xbf44bfb5,0x3f44bfb5,0xbfedbfb5,0xbfed0000,0x3f440000,0x3f444000,0xbfedc000,
0x3f44bfb5,0x3fed3fb5,0xbfedbfb5,0xbf44bfb5,0xbf153fb5,0x3f713fb5,0x3ff53fb5,0x3fe23fb5,0xbfa2bffb,0xbe493ec8,0xbfc63ec8,0x3fff3ffb,
0x3fff3f44,0xbfa2bf44,0xbe49bfed,0x3fc63fed,0xbf713f8e,0xbff5bfd5,0x3fe23fd5,0x3f153f8e,0x3fd50000,0x3ec80000,0xbf8ec000,0xbffbc000,
0x3ec83fed,0x3f8e3f44,0x3ffb3f44,0xbfd5bfed,0xbffbbfb5,0x3fd53fb5,0xbec83fb5,0xbf8ebfb5,0x3f8ebf44,0x3ffb3fed,0xbfd5bfed,0xbec8bf44,
0xbfffbfb5,0xbfc6bfb5,0xbe493fb5,0x3fa23fb5,0x3f15bf8e,0xbfe2bfd5,0xbff5bfd5,0x3f713f8e,0x3fe23fed,0xbff5bfed,0x3f71bf44,0x3f153f44,
0xbfa23ec8,0xbfffbffb,0x3fc63ffb,0x3e493ec8,0x80003f80,0x3f800000,0x80003f80,0x3f800000,0x80003f80,0x3f800000,0x80003f80,0x3f800000,
0x80003f80,0x3f800000,0x80003f80,0x3f800000,0x80003f80,0x3f800000,0x80003f80,0x3f800000,0x80003f80,0x3f800000,0x8000bf80,0xbf800000,
0x3f353f35,0x3f35bf35,0xbf35bf35,0xbf353f35,0x3f800000,0xbf80,0xbf800000,0x3f80,0x3f35bf35,0xbf35bf35,0xbf353f35,0x3f353f35,
0x80003f80,0x3f800000,0x80003f80,0x3f800000,0x3f800000,0xbf80,0x3f800000,0xbf80,0x8000bf80,0xbf800000,0x8000bf80,0xbf800000,
0xbf800000,0x3f80,0xbf800000,0x3f80,0x80003f80,0x3f800000,0x8000bf80,0xbf800000,0x3f35bf35,0xbf35bf35,0xbf353f35,0x3f353f35,
0xbf800000,0x3f80,0x3f800000,0xbf80,0x3f353f35,0x3f35bf35,0xbf35bf35,0xbf353f35,0x80003f80,0x3f800000,0x80003f80,0x3f800000,
0x8000bf80,0xbf800000,0x8000bf80,0xbf800000,0x80003f80,0x3f800000,0x80003f80,0x3f800000,0x8000bf80,0xbf800000,0x8000bf80,0xbf800000,
0x80003f80,0x3f800000,0x8000bf80,0xbf800000,0xbf35bf35,0xbf353f35,0x3f353f35,0x3f35bf35,0x3f800000,0xbf80,0xbf800000,0x3f80,
0xbf353f35,0x3f353f35,0x3f35bf35,0xbf35bf35,0x80003f80,0x3f800000,0x80003f80,0x3f800000,0xbf800000,0x3f80,0xbf800000,0x3f80,
0x8000bf80,0xbf800000,0x8000bf80,0xbf800000,0x3f800000,0xbf80,0x3f800000,0xbf80,0x80003f80,0x3f800000,0x8000bf80,0xbf800000,
0xbf353f35,0x3f353f35,0x3f35bf35,0xbf35bf35,0xbf800000,0x3f80,0x3f800000,0xbf80,0xbf35bf35,0xbf353f35,0x3f353f35,0x3f35bf35,
0x3f803f80,0x80008000,0x80008000,0xbf80bf80,0x3f803f80,0x80008000,0x80008000,0xbf80bf80,0x3f803f80,0x80008000,0x80008000,0xbf80bf80,
0x3f803f80,0x80008000,0x80008000,0xbf80bf80,0x3f353f80,0x3f358000,0x3f358000,0xbf35bf80,0xbf350000,0x3f353f80,0x3f353f80,0x3f358000,
0xbf35bf80,0xbf358000,0xbf358000,0x3f353f80,0x3f350000,0xbf35bf80,0xbf35bf80,0xbf358000,0x3f80,0x3f808000,0x3f808000,0x8000bf80,
0xbf80,0xbf808000,0xbf808000,0x80003f80,0x3f80,0x3f808000,0x3f808000,0x8000bf80,0xbf80,0xbf808000,0xbf808000,0x80003f80,
0xbf353f80,0x3f358000,0x3f358000,0x3f35bf80,0x3f350000,0x3f35bf80,0x3f35bf80,0xbf358000,0x3f35bf80,0xbf358000,0xbf358000,0xbf353f80,
0xbf350000,0xbf353f80,0xbf353f80,0x3f358000,0xbf803f80,0x80008000,0x80008000,0x3f80bf80,0xbf803f80,0x80008000,0x80008000,0x3f80bf80,
0xbf803f80,0x80008000,0x80008000,0x3f80bf80,0xbf803f80,0x80008000,0x80008000,0x3f80bf80,0xbf353f80,0xbf358000,0xbf358000,0x3f35bf80,
0x3f350000,0xbf353f80,0xbf353f80,0xbf358000,0x3f35bf80,0x3f358000,0x3f358000,0xbf353f80,0xbf350000,0x3f35bf80,0x3f35bf80,0x3f358000,
0x3f80,0xbf808000,0xbf808000,0x8000bf80,0xbf80,0x3f808000,0x3f808000,0x80003f80,0x3f80,0xbf808000,0xbf808000,0x8000bf80,
0xbf80,0x3f808000,0x3f808000,0x80003f80,0x3f353f80,0xbf358000,0xbf358000,0xbf35bf80,0xbf350000,0xbf35bf80,0xbf35bf80,0x3f358000,
0xbf35bf80,0x3f358000,0x3f358000,0x3f353f80,0x3f350000,0x3f353f80,0x3f353f80,0xbf358000,0x3f800000,0x0,0x3f800000,0x0,
0x3f800000,0x0,0x3f800000,0x0,0x3f800000,0x0,0x3f800000,0x0,0x3f800000,0x0,0x3f800000,0x0,
0x3f800000,0x0,0x3f7fb10f,0xbd48fb30,0x3f7ec46d,0xbdc8bd36,0x3f7d3aac,0xbe164083,0x3f7b14be,0xbe47c5c2,0x3f7853f8,0xbe78cfcc,
0x3f74fa0b,0xbe94a031,0x3f710908,0xbeac7cd4,0x3f800000,0x0,0x3f7ec46d,0xbdc8bd36,0x3f7b14be,0xbe47c5c2,0x3f74fa0b,0xbe94a031,
0x3f6c835e,0xbec3ef15,0x3f61c598,0xbef15aea,0x3f54db31,0xbf0e39da,0x3f45e403,0xbf226799,0x3f800000,0x0,0x3f7d3aac,0xbe164083,
0x3f74fa0b,0xbe94a031,0x3f676bd8,0xbedae880,0x3f54db31,0xbf0e39da,0x3f3daef9,0xbf2beb4a,0x3f226799,0xbf45e403,0x3f039c3d,0xbf5b941a,
0x3f800000,0x0,0x3f7b14be,0xbe47c5c2,0x3f6c835e,0xbec3ef15,0x3f54db31,0xbf0e39da,0x3f3504f3,0xbf3504f3,0x3f0e39da,0xbf54db31,
0x3ec3ef15,0xbf6c835e,0x3e47c5c2,0xbf7b14be,0x3f800000,0x0,0x3f7853f8,0xbe78cfcc,0x3f61c598,0xbef15aea,0x3f3daef9,0xbf2beb4a,
0x3f0e39da,0xbf54db31,0x3eac7cd4,0xbf710908,0x3dc8bd36,0xbf7ec46d,0xbe164083,0xbf7d3aac,0x3f800000,0x0,0x3f74fa0b,0xbe94a031,
0x3f54db31,0xbf0e39da,0x3f226799,0xbf45e403,0x3ec3ef15,0xbf6c835e,0x3dc8bd36,0xbf7ec46d,0xbe47c5c2,0xbf7b14be,0xbef15aea,0xbf61c598,
0x3f800000,0x0,0x3f710908,0xbeac7cd4,0x3f45e403,0xbf226799,0x3f039c3d,0xbf5b941a,0x3e47c5c2,0xbf7b14be,0xbe164083,0xbf7d3aac,
0xbef15aea,0xbf61c598,0xbf3daef9,0xbf2beb4a,0x3f800000,0x0,0x3f800000,0x0,0x3f800000,0x0,0x3f800000,0x0,
0x3f800000,0x0,0x3f800000,0x0,0x3f800000,0x0,0x3f800000,0x0,0x3f6c835e,0xbec3ef15,0x3f676bd8,0xbedae880,
0x3f61c598,0xbef15aea,0x3f5b941a,0xbf039c3d,0x3f54db31,0xbf0e39da,0x3f4d9f02,0xbf187fc0,0x3f45e403,0xbf226799,0x3f3daef9,0xbf2beb4a,
0x3f3504f3,0xbf3504f3,0x3f226799,0xbf45e403,0x3f0e39da,0xbf54db31,0x3ef15aea,0xbf61c598,0x3ec3ef15,0xbf6c835e,0x3e94a031,0xbf74fa0b,
0x3e47c5c2,0xbf7b14be,0x3dc8bd36,0xbf7ec46d,0x3ec3ef15,0xbf6c835e,0x3e78cfcc,0xbf7853f8,0x3dc8bd36,0xbf7ec46d,0xbd48fb30,0xbf7fb10f,
0xbe47c5c2,0xbf7b14be,0xbeac7cd4,0xbf710908,0xbef15aea,0xbf61c598,0xbf187fc0,0xbf4d9f02,0x0,0xbf800000,0xbe47c5c2,0xbf7b14be,
0xbec3ef15,0xbf6c835e,0xbf0e39da,0xbf54db31,0xbf3504f3,0xbf3504f3,0xbf54db31,0xbf0e39da,0xbf6c835e,0xbec3ef15,0xbf7b14be,0xbe47c5c2,
0xbec3ef15,0xbf6c835e,0xbf187fc0,0xbf4d9f02,0xbf45e403,0xbf226799,0xbf676bd8,0xbedae880,0xbf7b14be,0xbe47c5c2,0xbf7fb10f,0x3d48fb30,
0xbf74fa0b,0x3e94a031,0xbf5b941a,0x3f039c3d,0xbf3504f3,0xbf3504f3,0xbf61c598,0xbef15aea,0xbf7b14be,0xbe47c5c2,0xbf7ec46d,0x3dc8bd36,
0xbf6c835e,0x3ec3ef15,0xbf45e403,0x3f226799,0xbf0e39da,0x3f54db31,0xbe94a031,0x3f74fa0b,0xbf6c835e,0xbec3ef15,0xbf7fb10f,0xbd48fb30,
0xbf74fa0b,0x3e94a031,0xbf4d9f02,0x3f187fc0,0xbf0e39da,0x3f54db31,0xbe78cfcc,0x3f7853f8,0x3dc8bd36,0x3f7ec46d,0x3edae880,0x3f676bd8,
0x80003f80,0x3f800000,0x3f800000,0xbf80,0x3ec43f6d,0x3f6dbec4,0x3f6dbec4,0xbec4bf6d,0x3f353f35,0x3f35bf35,0x3f35bf35,0xbf35bf35,
0x3f6d3ec4,0x3ec4bf6d,0x3ec4bf6d,0xbf6dbec4,0x80003f80,0x3f800000,0xbf800000,0x3f80,0x3f6d3ec4,0x3ec4bf6d,0xbec43f6d,0x3f6d3ec4,
0x3f35bf35,0xbf35bf35,0x3f353f35,0x3f35bf35,0xbec4bf6d,0xbf6d3ec4,0x3f6dbec4,0xbec4bf6d,0x80003f80,0x3f800000,0x3f800000,0xbf80,
0x3f6dbec4,0xbec4bf6d,0xbec4bf6d,0xbf6d3ec4,0xbf35bf35,0xbf353f35,0xbf353f35,0x3f353f35,0xbec43f6d,0x3f6d3ec4,0x3f6d3ec4,0x3ec4bf6d,
0x80003f80,0x3f800000,0xbf800000,0x3f80,0x3ec4bf6d,0xbf6dbec4,0x3f6d3ec4,0x3ec4bf6d,0xbf353f35,0x3f353f35,0xbf35bf35,0xbf353f35,
0x3f6dbec4,0xbec4bf6d,0x3ec43f6d,0x3f6dbec4,0x80003f80,0x3f800000,0x3f800000,0xbf80,0xbec4bf6d,0xbf6d3ec4,0xbf6d3ec4,0x3ec43f6d,
0x3f353f35,0x3f35bf35,0x3f35bf35,0xbf35bf35,0xbf6dbec4,0xbec43f6d,0xbec43f6d,0x3f6d3ec4,0x80003f80,0x3f800000,0xbf800000,0x3f80,
0xbf6dbec4,0xbec43f6d,0x3ec4bf6d,0xbf6dbec4,0x3f35bf35,0xbf35bf35,0x3f353f35,0x3f35bf35,0x3ec43f6d,0x3f6dbec4,0xbf6d3ec4,0x3ec43f6d,
0x80003f80,0x3f800000,0x3f800000,0xbf80,0xbf6d3ec4,0x3ec43f6d,0x3ec43f6d,0x3f6dbec4,0xbf35bf35,0xbf353f35,0xbf353f35,0x3f353f35,
0x3ec4bf6d,0xbf6dbec4,0xbf6dbec4,0xbec43f6d,0x80003f80,0x3f800000,0xbf800000,0x3f80,0xbec43f6d,0x3f6d3ec4,0xbf6dbec4,0xbec43f6d,
0xbf353f35,0x3f353f35,0xbf35bf35,0xbf353f35,0xbf6d3ec4,0x3ec43f6d,0xbec4bf6d,0xbf6d3ec4,0x3f803f80,0x80008000,0x80008000,0xbf80bf80,
0x3f803f80,0x80008000,0x80008000,0xbf80bf80,0x3f803f80,0x80008000,0x80008000,0xbf80bf80,0x3f803f80,0x80008000,0x80008000,0xbf80bf80,
0x3ec43f6d,0x3f6d3ec4,0x3f6d3ec4,0xbec4bf6d,0xbf6dbec4,0x3ec43f6d,0x3ec43f6d,0x3f6d3ec4,0xbec4bf6d,0xbf6dbec4,0xbf6dbec4,0x3ec43f6d,
0x3f6d3ec4,0xbec4bf6d,0xbec4bf6d,0xbf6dbec4,0xbf353f35,0x3f353f35,0x3f353f35,0x3f35bf35,0x3f35bf35,0xbf35bf35,0xbf35bf35,0xbf353f35,
0xbf353f35,0x3f353f35,0x3f353f35,0x3f35bf35,0x3f35bf35,0xbf35bf35,0xbf35bf35,0xbf353f35,0xbf6d3ec4,0xbec43f6d,0xbec43f6d,0x3f6dbec4,
0xbec43f6d,0x3f6dbec4,0x3f6dbec4,0x3ec4bf6d,0x3f6dbec4,0x3ec4bf6d,0x3ec4bf6d,0xbf6d3ec4,0x3ec4bf6d,0xbf6d3ec4,0xbf6d3ec4,0xbec43f6d,
0x0,0xbf803f80,0xbf803f80,0x80008000,0x0,0xbf803f80,0xbf803f80,0x80008000,0x0,0xbf803f80,0xbf803f80,0x80008000,
0x0,0xbf803f80,0xbf803f80,0x80008000,0x3f6dbec4,0xbec43f6d,0xbec43f6d,0xbf6d3ec4,0x3ec4bf6d,0x3f6dbec4,0x3f6dbec4,0xbec43f6d,
0xbf6d3ec4,0x3ec4bf6d,0x3ec4bf6d,0x3f6dbec4,0xbec43f6d,0xbf6d3ec4,0xbf6d3ec4,0x3ec4bf6d,0x3f35bf35,0x3f353f35,0x3f353f35,0xbf353f35,
0xbf353f35,0xbf35bf35,0xbf35bf35,0x3f35bf35,0x3f35bf35,0x3f353f35,0x3f353f35,0xbf353f35,0xbf353f35,0xbf35bf35,0xbf35bf35,0x3f35bf35,
0xbec4bf6d,0x3f6d3ec4,0x3f6d3ec4,0x3ec43f6d,0x3f6d3ec4,0x3ec43f6d,0x3ec43f6d,0xbf6dbec4,0x3ec43f6d,0xbf6dbec4,0xbf6dbec4,0xbec4bf6d,
0xbf6dbec4,0xbec4bf6d,0xbec4bf6d,0x3f6d3ec4,0x3f800000,0x0,0x3f7fec43,0xbcc90ab0,0x3f7fb10f,0xbd48fb30,0x3f7f4e6d,0xbd96a905,
0x3f7ec46d,0xbdc8bd36,0x3f7e1324,0xbdfab273,0x3f7d3aac,0xbe164083,0x3f7c3b28,0xbe2f10a2,0x3f800000,0x0,0x3f7f4e6d,0xbd96a905,
0x3f7d3aac,0xbe164083,0x3f79c79d,0xbe605c13,0x3f74fa0b,0xbe94a031,0x3f6ed89e,0xbeb8442a,0x3f676bd8,0xbedae880,0x3f5ebe05,0xbefc5d27,
0x3f800000,0x0,0x3f7e1324,0xbdfab273,0x3f7853f8,0xbe78cfcc,0x3f6ed89e,0xbeb8442a,0x3f61c598,0xbef15aea,0x3f514d3d,0xbf13682a,
0x3f3daef9,0xbf2beb4a,0x3f273656,0xbf41d870,0x3f800000,0x0,0x3f7c3b28,0xbe2f10a2,0x3f710908,0xbeac7cd4,0x3f5ebe05,0xbefc5d27,
0x3f45e403,0xbf226799,0x3f273656,0xbf41d870,0x3f039c3d,0xbf5b941a,0x3eb8442a,0xbf6ed89e,0x3f800000,0x0,0x3f79c79d,0xbe605c13,
0x3f676bd8,0xbedae880,0x3f49d112,0xbf1d7fd1,0x3f226799,0xbf45e403,0x3ee63375,0xbf64aa59,0x3e78cfcc,0xbf7853f8,0x3cc90ab0,0xbf7fec43,
0x3f800000,0x0,0x3f76ba07,0xbe888e93,0x3f5b941a,0xbf039c3d,0x3f3085bb,0xbf396842,0x3ef15aea,0xbf61c598,0x3e605c13,0xbf79c79d,
0xbd48fb30,0xbf7fb10f,0xbea09ae5,0xbf731447,0x3f800000,0x0,0x3f731447,0xbea09ae5,0x3f4d9f02,0xbf187fc0,0x3f13682a,0xbf514d3d,
0x3e94a031,0xbf74fa0b,0xbcc90ab0,0xbf7fec43,0xbeac7cd4,0xbf710908,0xbf1d7fd1,0xbf49d112,0x3f800000,0x0,0x3f6ed89e,0xbeb8442a,
0x3f3daef9,0xbf2beb4a,0x3ee63375,0xbf64aa59,0x3dc8bd36,0xbf7ec46d,0xbe888e93,0xbf76ba07,0xbf187fc0,0xbf4d9f02,0xbf584853,0xbf08f59b,
0x3f7b14be,0xbe47c5c2,0x3f79c79d,0xbe605c13,0x3f7853f8,0xbe78cfcc,0x3f76ba07,0xbe888e93,0x3f74fa0b,0xbe94a031,0x3f731447,0xbea09ae5,
0x3f710908,0xbeac7cd4,0x3f6ed89e,0xbeb8442a,0x3f54db31,0xbf0e39da,0x3f49d112,0xbf1d7fd1,0x3f3daef9,0xbf2beb4a,0x3f3085bb,0xbf396842,
0x3f226799,0xbf45e403,0x3f13682a,0xbf514d3d,0x3f039c3d,0xbf5b941a,0x3ee63375,0xbf64aa59,0x3f0e39da,0xbf54db31,0x3ee63375,0xbf64aa59,
0x3eac7cd4,0xbf710908,0x3e605c13,0xbf79c79d,0x3dc8bd36,0xbf7ec46d,0xbcc90ab0,0xbf7fec43,0xbe164083,0xbf7d3aac,0xbe888e93,0xbf76ba07,
0x3e47c5c2,0xbf7b14be,0x3cc90ab0,0xbf7fec43,0xbe164083,0xbf7d3aac,0xbea09ae5,0xbf731447,0xbef15aea,0xbf61c598,0xbf1d7fd1,0xbf49d112,
0xbf3daef9,0xbf2beb4a,0xbf584853,0xbf08f59b,0xbe47c5c2,0xbf7b14be,0xbecf7bca,0xbf6a09a7,0xbf187fc0,0xbf4d9f02,0xbf41d870,0xbf273656,
0xbf61c598,0xbef15aea,0xbf76ba07,0xbe888e93,0xbf7fb10f,0xbd48fb30,0xbf7c3b28,0x3e2f10a2,0xbf0e39da,0xbf54db31,0xbf41d870,0xbf273656,
0xbf676bd8,0xbedae880,0xbf7c3b28,0xbe2f10a2,0xbf7ec46d,0x3dc8bd36,0xbf6ed89e,0x3eb8442a,0xbf4d9f02,0x3f187fc0,0xbf1d7fd1,0x3f49d112,
0xbf54db31,0xbf0e39da,0xbf76ba07,0xbe888e93,0xbf7fb10f,0x3d48fb30,0xbf6ed89e,0x3eb8442a,0xbf45e403,0x3f226799,0xbf08f59b,0x3f584853,
0xbe78cfcc,0x3f7853f8,0x3d96a905,0x3f7f4e6d,0xbf7b14be,0xbe47c5c2,0xbf7c3b28,0x3e2f10a2,0xbf5b941a,0x3f039c3d,0xbf1d7fd1,0x3f49d112,
0xbe94a031,0x3f74fa0b,0x3d96a905,0x3f7f4e6d,0x3edae880,0x3f676bd8,0x3f396842,0x3f3085bb,0x80003f80,0x80003f80,0x80003f80,0x80003f80,
0x80003f80,0x80003f80,0x80003f80,0x80003f80,0x80003f80,0x80003f80,0x80003f80,0x80003f80,0x80003f80,0x80003f80,0x80003f80,0x80003f80,
0x3f800000,0x3f800000,0x3f800000,0x3f800000,0x3f800000,0x3f800000,0x3f800000,0x3f800000,0x3f800000,0x3f800000,0x3f800000,0x3f800000,
0x3f800000,0x3f800000,0x3f800000,0x3f800000,0x80003f80,0x3f353f35,0x80003f80,0x3f353f35,0x3f800000,0x3f35bf35,0x3f800000,0x3f35bf35,
0x8000bf80,0xbf35bf35,0x8000bf80,0xbf35bf35,0xbf800000,0xbf353f35,0xbf800000,0xbf353f35,0x3f800000,0x3f35bf35,0x3f800000,0x3f35bf35,
0xbf80,0xbf35bf35,0xbf80,0xbf35bf35,0xbf800000,0xbf353f35,0xbf800000,0xbf353f35,0x3f80,0x3f353f35,0x3f80,0x3f353f35,
0x80003f80,0x3f800000,0x80003f80,0x3f800000,0x8000bf80,0xbf800000,0x8000bf80,0xbf800000,0x80003f80,0x3f800000,0x80003f80,0x3f800000,
0x8000bf80,0xbf800000,0x8000bf80,0xbf800000,0x3f800000,0xbf80,0x3f800000,0xbf80,0xbf800000,0x3f80,0xbf800000,0x3f80,
0x3f800000,0xbf80,0x3f800000,0xbf80,0xbf800000,0x3f80,0xbf800000,0x3f80,0x80003f80,0x3f35bf35,0x80003f80,0x3f35bf35,
0xbf800000,0x3f353f35,0xbf800000,0x3f353f35,0x8000bf80,0xbf353f35,0x8000bf80,0xbf353f35,0x3f800000,0xbf35bf35,0x3f800000,0xbf35bf35,
0x3f800000,0xbf35bf35,0x3f800000,0xbf35bf35,0x3f80,0x3f35bf35,0x3f80,0x3f35bf35,0xbf800000,0x3f353f35,0xbf800000,0x3f353f35,
0xbf80,0xbf353f35,0xbf80,0xbf353f35,0x80003f80,0x3ec43f6d,0x8000bf80,0xbec4bf6d,0x3f353f35,0x3f6d3ec4,0xbf35bf35,0xbf6dbec4,
0x3f800000,0x3f6dbec4,0xbf800000,0xbf6d3ec4,0x3f35bf35,0x3ec4bf6d,0xbf353f35,0xbec43f6d,0x3f800000,0x3f6dbec4,0xbf800000,0xbf6d3ec4,
0x3f35bf35,0x3ec4bf6d,0xbf353f35,0xbec43f6d,0xbf80,0xbec4bf6d,0x3f80,0x3ec43f6d,0xbf35bf35,0xbf6dbec4,0x3f353f35,0x3f6d3ec4,
0x80003f80,0x3f6d3ec4,0x8000bf80,0xbf6dbec4,0x3f35bf35,0xbec4bf6d,0xbf353f35,0x3ec43f6d,0xbf800000,0xbec43f6d,0x3f800000,0x3ec4bf6d,
0x3f353f35,0x3f6dbec4,0xbf35bf35,0xbf6d3ec4,0x3f800000,0x3ec4bf6d,0xbf800000,0xbec43f6d,0xbf35bf35,0xbf6d3ec4,0x3f353f35,0x3f6dbec4,
0x3f80,0x3f6d3ec4,0xbf80,0xbf6dbec4,0x3f35bf35,0xbec4bf6d,0xbf353f35,0x3ec43f6d,0x80003f80,0x3f6dbec4,0x8000bf80,0xbf6d3ec4,
0xbf35bf35,0xbec43f6d,0x3f353f35,0x3ec4bf6d,0x3f800000,0xbec4bf6d,0xbf800000,0x3ec43f6d,0xbf353f35,0x3f6d3ec4,0x3f35bf35,0xbf6dbec4,
0x3f800000,0xbec4bf6d,0xbf800000,0x3ec43f6d,0xbf353f35,0x3f6d3ec4,0x3f35bf35,0xbf6dbec4,0xbf80,0xbf6d3ec4,0x3f80,0x3f6dbec4,
0x3f353f35,0x3ec4bf6d,0xbf35bf35,0xbec43f6d,0x80003f80,0x3ec4bf6d,0x8000bf80,0xbec43f6d,0xbf353f35,0x3f6dbec4,0x3f35bf35,0xbf6d3ec4,
0xbf800000,0x3f6d3ec4,0x3f800000,0xbf6dbec4,0xbf35bf35,0x3ec43f6d,0x3f353f35,0xbec4bf6d,0x3f800000,0xbf6dbec4,0xbf800000,0x3f6d3ec4,
0x3f353f35,0xbec4bf6d,0xbf35bf35,0x3ec43f6d,0x3f80,0x3ec4bf6d,0xbf80,0xbec43f6d,0xbf353f35,0x3f6dbec4,0x3f35bf35,0xbf6d3ec4,
0x80003f80,0x8000bf80,0x80003f80,0x8000bf80,0x80003f80,0x8000bf80,0x80003f80,0x8000bf80,0x80003f80,0x8000bf80,0x80003f80,0x8000bf80,
0x80003f80,0x8000bf80,0x80003f80,0x8000bf80,0x3f800000,0xbf800000,0x3f800000,0xbf800000,0x3f800000,0xbf800000,0x3f800000,0xbf800000,
0x3f800000,0xbf800000,0x3f800000,0xbf800000,0x3f800000,0xbf800000,0x3f800000,0xbf800000,0x80003f80,0xbf35bf35,0x80003f80,0xbf35bf35,
0x3f800000,0xbf353f35,0x3f800000,0xbf353f35,0x8000bf80,0x3f353f35,0x8000bf80,0x3f353f35,0xbf800000,0x3f35bf35,0xbf800000,0x3f35bf35,
0x3f800000,0xbf353f35,0x3f800000,0xbf353f35,0xbf80,0x3f353f35,0xbf80,0x3f353f35,0xbf800000,0x3f35bf35,0xbf800000,0x3f35bf35,
0x3f80,0xbf35bf35,0x3f80,0xbf35bf35,0x80003f80,0xbf800000,0x80003f80,0xbf800000,0x8000bf80,0x3f800000,0x8000bf80,0x3f800000,
0x80003f80,0xbf800000,0x80003f80,0xbf800000,0x8000bf80,0x3f800000,0x8000bf80,0x3f800000,0x3f800000,0x3f80,0x3f800000,0x3f80,
0xbf800000,0xbf80,0xbf800000,0xbf80,0x3f800000,0x3f80,0x3f800000,0x3f80,0xbf800000,0xbf80,0xbf800000,0xbf80,
0x80003f80,0xbf353f35,0x80003f80,0xbf353f35,0xbf800000,0xbf35bf35,0xbf800000,0xbf35bf35,0x8000bf80,0x3f35bf35,0x8000bf80,0x3f35bf35,
0x3f800000,0x3f353f35,0x3f800000,0x3f353f35,0x3f800000,0x3f353f35,0x3f800000,0x3f353f35,0x3f80,0xbf353f35,0x3f80,0xbf353f35,
0xbf800000,0xbf35bf35,0xbf800000,0xbf35bf35,0xbf80,0x3f35bf35,0xbf80,0x3f35bf35,0x80003f80,0xbec4bf6d,0x8000bf80,0x3ec43f6d,
0x3f353f35,0xbf6dbec4,0xbf35bf35,0x3f6d3ec4,0x3f800000,0xbf6d3ec4,0xbf800000,0x3f6dbec4,0x3f35bf35,0xbec43f6d,0xbf353f35,0x3ec4bf6d,
0x3f800000,0xbf6d3ec4,0xbf800000,0x3f6dbec4,0x3f35bf35,0xbec43f6d,0xbf353f35,0x3ec4bf6d,0xbf80,0x3ec43f6d,0x3f80,0xbec4bf6d,
0xbf35bf35,0x3f6d3ec4,0x3f353f35,0xbf6dbec4,0x80003f80,0xbf6dbec4,0x8000bf80,0x3f6d3ec4,0x3f35bf35,0x3ec43f6d,0xbf353f35,0xbec4bf6d,
0xbf800000,0x3ec4bf6d,0x3f800000,0xbec43f6d,0x3f353f35,0xbf6d3ec4,0xbf35bf35,0x3f6dbec4,0x3f800000,0xbec43f6d,0xbf800000,0x3ec4bf6d,
0xbf35bf35,0x3f6dbec4,0x3f353f35,0xbf6d3ec4,0x3f80,0xbf6dbec4,0xbf80,0x3f6d3ec4,0x3f35bf35,0x3ec43f6d,0xbf353f35,0xbec4bf6d,
0x80003f80,0xbf6d3ec4,0x8000bf80,0x3f6dbec4,0xbf35bf35,0x3ec4bf6d,0x3f353f35,0xbec43f6d,0x3f800000,0x3ec43f6d,0xbf800000,0xbec4bf6d,
0xbf353f35,0xbf6dbec4,0x3f35bf35,0x3f6d3ec4,0x3f800000,0x3ec43f6d,0xbf800000,0xbec4bf6d,0xbf353f35,0xbf6dbec4,0x3f35bf35,0x3f6d3ec4,
0xbf80,0x3f6dbec4,0x3f80,0xbf6d3ec4,0x3f353f35,0xbec43f6d,0xbf35bf35,0x3ec4bf6d,0x80003f80,0xbec43f6d,0x8000bf80,0x3ec4bf6d,
0xbf353f35,0xbf6d3ec4,0x3f35bf35,0x3f6dbec4,0xbf800000,0xbf6dbec4,0x3f800000,0x3f6d3ec4,0xbf35bf35,0xbec4bf6d,0x3f353f35,0x3ec43f6d,
0x3f800000,0x3f6d3ec4,0xbf800000,0xbf6dbec4,0x3f353f35,0x3ec43f6d,0xbf35bf35,0xbec4bf6d,0x3f80,0xbec43f6d,0xbf80,0x3ec4bf6d,
0xbf353f35,0xbf6d3ec4,0x3f35bf35,0x3f6dbec4,
};
constexpr int TB_F = 0, TB_E = 512, TB_P2 = 1024;

enum { C_EP = 0, C_Z1 = 32, C_Z2 = 96, C_H3 = 128, C_U = 160, C_X = 288, C_TOTAL = 512 };
struct Scratch {
  unsigned cnt[C_TOTAL];
  uint32_t moda[8 * 2 * D_];
  uint32_t mod[4 * D_ + 256];
  uint32_t z1[120 * 5120];
  uint32_t z2[128 * 4800];
  uint8_t h3[32 * 18 * 4096];
  uint8_t u[72 * D_ * 128];
};
__device__ __align__(1024) Scratch g_s;

#define HOLDA 5
#define GOAT 0
#define H3W 0
#define X1K 10
#define PEEK 1
#ifndef NV1
#define NV1 12
#endif
#ifndef NV2
#define NV2 20
#endif
#define GDEP 3
#define TRK0 50
#define W0N 3
#define TRKC 350
#define HD1 150
#define STRESS 0
#define GV 0
#define EH 7
#define KNOB0 0

#define FAILCNT(k) do {} while (0)
#define CK(k) do {} while (0)
#define CKX(k) do {} while (0)
#define TS(k) do {} while (0)
#define TSC(k) do {} while (0)
struct Maps { CUtensorMap z1, z2[2], w1a, w1b, h3, w2, wf[4], wm; };
struct Params {
  const __nv_bfloat16 *x, *c, *wmod;
  Scratch* s;
  const uint4* tab;
  const __nv_bfloat16 *wr, *wi, *w1, *w2, *b1, *b2;
  uint32_t* out;
};

__device__ __forceinline__ uint32_t smem_u32(const void* p) { return (uint32_t)__cvta_generic_to_shared(p); }
__device__ __forceinline__ void mbar_init(uint32_t b, int c) { asm volatile("mbarrier.init.shared::cta.b64 [%0], %1;" ::"r"(b), "r"(c)); }
__device__ __forceinline__ void mbar_expect(uint32_t b, int bytes) { asm volatile("mbarrier.arrive.expect_tx.shared::cta.b64 _, [%0], %1;" ::"r"(b), "r"(bytes) : "memory"); }
__device__ __forceinline__ void mbar_arrive(uint32_t b) { asm volatile("mbarrier.arrive.shared::cta.b64 _, [%0];" ::"r"(b) : "memory"); }
#define MBAR_WAIT(SEM)                                                                                                         \
  asm volatile("{\n.reg .pred p;\n.reg .u32 it;\nmov.u32 it, 0;\nW:\nmbarrier.try_wait.parity" SEM ".shared::cta.b64 p, [%0], %1;\n" \
               "@p bra.uni D;\nadd.u32 it, it, 1;\nsetp.lt.u32 p, it, 0x400000;\n@p bra.uni W;\ntrap;\nD:\n}" ::"r"(b), "r"(ph) : "memory")
__device__ __forceinline__ void mbar_wait(uint32_t b, int ph) { MBAR_WAIT(""); }
__device__ __forceinline__ uint32_t mbar_test(uint32_t b, int ph) {
  uint32_t ok;
  asm volatile("{\n.reg .pred p;\nmbarrier.test_wait.parity.shared::cta.b64 p, [%1], %2;\nselp.u32 %0, 1, 0, p;\n}\n" : "=r"(ok) : "r"(b), "r"(ph) : "memory");
  return ok;
}
__device__ __forceinline__ void tma2d(uint32_t dst, const CUtensorMap* m, int c0, int c1, uint32_t bar) {
  asm volatile("cp.async.bulk.tensor.2d.shared::cluster.global.mbarrier::complete_tx::bytes [%0], [%1, {%3, %4}], [%2];" ::"r"(dst), "l"(m), "r"(bar), "r"(c0), "r"(c1) : "memory");
}
__device__ __forceinline__ uint64_t pol_ef() { uint64_t p; asm("createpolicy.fractional.L2::evict_first.b64 %0, 1.0;" : "=l"(p)); return p; }
__device__ __forceinline__ void tma3d_ef(uint32_t dst, const CUtensorMap* m, int c1, int c2, uint32_t bar) {
  asm volatile("cp.async.bulk.tensor.3d.shared::cluster.global.mbarrier::complete_tx::bytes.L2::cache_hint [%0], [%1, {%3, %4, %5}], [%2], %6;" ::"r"(dst), "l"(m), "r"(bar), "r"(0), "r"(c1), "r"(c2), "l"(pol_ef()) : "memory");
}
__device__ __forceinline__ void tma4d_ef(uint32_t dst, const CUtensorMap* m, int c1, int c2, int c3, uint32_t bar) {
  asm volatile("cp.async.bulk.tensor.4d.shared::cluster.global.mbarrier::complete_tx::bytes.L2::cache_hint [%0], [%1, {%3, %7, %4, %5}], [%2], %6;" ::"r"(dst), "l"(m), "r"(bar), "r"(0), "r"(c2), "r"(c3), "l"(pol_ef()), "r"(c1) : "memory");
}
__device__ __forceinline__ void bulk_ld(uint32_t dst, const void* src, int bytes, uint32_t bar) {
  asm volatile("cp.async.bulk.shared::cluster.global.mbarrier::complete_tx::bytes [%0], [%1], %2, [%3];" ::"r"(dst), "l"(src), "r"(bytes), "r"(bar) : "memory");
}
__device__ __forceinline__ void bulk_st(void* dst, uint32_t src, int bytes) {
  asm volatile("cp.async.bulk.global.shared::cta.bulk_group [%0], [%1], %2;" ::"l"(dst), "r"(src), "r"(bytes) : "memory");
}
__device__ __forceinline__ void tma_st2d(const CUtensorMap* m, uint32_t src, int c0, int c1) {
  asm volatile("cp.async.bulk.tensor.2d.global.shared::cta.bulk_group [%0, {%2, %3}], [%1];" ::"l"(m), "r"(src), "r"(c0), "r"(c1) : "memory");
}
__device__ __forceinline__ void tma_st3d(const CUtensorMap* m, uint32_t src, int c0, int c1, int c2) {
  asm volatile("cp.async.bulk.tensor.3d.global.shared::cta.bulk_group [%0, {%2, %3, %4}], [%1];" ::"l"(m), "r"(src), "r"(c0), "r"(c1), "r"(c2) : "memory");
}
__device__ __forceinline__ void bulk_commit_wait_read() {
  asm volatile("cp.async.bulk.commit_group;" ::: "memory");
  asm volatile("cp.async.bulk.wait_group.read 0;" ::: "memory");
}
__device__ __forceinline__ void bulk_commit_wait() {
  asm volatile("cp.async.bulk.commit_group;" ::: "memory");
  asm volatile("cp.async.bulk.wait_group 0;" ::: "memory");
}
__device__ __forceinline__ void prefetch_l2(const void* p, int bytes) {
  asm volatile("cp.async.bulk.prefetch.L2.global [%0], %1;" ::"l"(p), "r"(bytes) : "memory");
}
__device__ __forceinline__ void wg_fence() { asm volatile("wgmma.fence.sync.aligned;" ::: "memory"); }
__device__ __forceinline__ void wg_commit() { asm volatile("wgmma.commit_group.sync.aligned;" ::: "memory"); }
template <int N> __device__ __forceinline__ void wg_wait() { asm volatile("wgmma.wait_group.sync.aligned %0;" ::"n"(N) : "memory"); }
template <int N> __device__ __forceinline__ void reg_fence(float (&d)[N]) {
#pragma unroll
  for (int i = 0; i < N; i++) asm volatile("" : "+f"(d[i])::"memory");
}
__device__ __forceinline__ void fence_async_smem() { asm volatile("fence.proxy.async.shared::cta;" ::: "memory"); }
__device__ __forceinline__ void fence_async_glb() { asm volatile("fence.proxy.async.global;" ::: "memory"); }
__device__ __forceinline__ uint32_t ld_rlx(const void* p) { uint32_t v; asm volatile("ld.relaxed.gpu.global.b32 %0, [%1];" : "=r"(v) : "l"(p) : "memory"); return v; }
__device__ __forceinline__ uint2 ld_rlx2(const void* p) { uint2 v; asm volatile("ld.relaxed.gpu.global.v2.b32 {%0,%1}, [%2];" : "=r"(v.x), "=r"(v.y) : "l"(p) : "memory"); return v; }
__device__ __forceinline__ uint4 ld_rlx4(const void* p) { uint4 v; asm volatile("ld.relaxed.gpu.global.v4.b32 {%0,%1,%2,%3}, [%4];" : "=r"(v.x), "=r"(v.y), "=r"(v.z), "=r"(v.w) : "l"(p) : "memory"); return v; }
__device__ __forceinline__ uint32_t ld_nc(const void* p) { uint32_t v; asm volatile("ld.global.nc.L1::no_allocate.b32 %0, [%1];" : "=r"(v) : "l"(p) : "memory"); return v; }
__device__ __forceinline__ uint4 ld_nc4(const void* p) { uint4 v; asm volatile("ld.global.nc.v4.b32 {%0,%1,%2,%3}, [%4];" : "=r"(v.x), "=r"(v.y), "=r"(v.z), "=r"(v.w) : "l"(p) : "memory"); return v; }
__device__ __forceinline__ uint32_t lds(uint32_t a) { uint32_t v; asm volatile("ld.shared.b32 %0, [%1];" : "=r"(v) : "r"(a) : "memory"); return v; }
__device__ __forceinline__ uint2 lds2(uint32_t a) { uint2 v; asm volatile("ld.shared.v2.b32 {%0,%1}, [%2];" : "=r"(v.x), "=r"(v.y) : "r"(a) : "memory"); return v; }
__device__ __forceinline__ void lds2_if(int on, uint2& v, uint32_t a) { asm volatile("{\n.reg .pred p;\nsetp.ne.u32 p, %3, 0;\n@p ld.shared.v2.b32 {%0,%1}, [%2];\n}" : "+r"(v.x), "+r"(v.y) : "r"(a), "r"(on) : "memory"); }
__device__ __forceinline__ uint4 lds4(uint32_t a) { uint4 v; asm volatile("ld.shared.v4.b32 {%0,%1,%2,%3}, [%4];" : "=r"(v.x), "=r"(v.y), "=r"(v.z), "=r"(v.w) : "r"(a) : "memory"); return v; }
__device__ __forceinline__ float lds_bf(uint32_t a) { uint32_t v; asm volatile("ld.shared.u16 %0, [%1];" : "=r"(v) : "r"(a) : "memory"); return __uint_as_float(v << 16); }
__device__ __forceinline__ void sts(uint32_t a, uint32_t v) { asm volatile("st.shared.b32 [%0], %1;" ::"r"(a), "r"(v) : "memory"); }
__device__ __forceinline__ void sts2(uint32_t a, uint32_t v0, uint32_t v1) { asm volatile("st.shared.v2.b32 [%0], {%1,%2};" ::"r"(a), "r"(v0), "r"(v1) : "memory"); }
__device__ __forceinline__ void sts4(uint32_t a, uint32_t v0, uint32_t v1, uint32_t v2, uint32_t v3) { asm volatile("st.shared.v4.b32 [%0], {%1,%2,%3,%4};" ::"r"(a), "r"(v0), "r"(v1), "r"(v2), "r"(v3) : "memory"); }
__device__ __forceinline__ void bar_sync(int id, int n) { asm volatile("bar.sync %0, %1;" ::"r"(id), "r"(n) : "memory"); }
__device__ __forceinline__ void bar_arrive(int id, int n) { asm volatile("bar.arrive %0, %1;" ::"r"(id), "r"(n) : "memory"); }
__device__ __forceinline__ void red_add(unsigned* p, unsigned v) { asm volatile("red.relaxed.gpu.global.add.u32 [%0], %1;" ::"l"(p), "r"(v) : "memory"); }
__device__ __forceinline__ bool any(bool p) { return __any_sync(0xffffffffu, p); }
__device__ __forceinline__ void pause(unsigned clks) {
  asm volatile("{\n.reg .pred p;\n.reg .u32 a, b;\nmov.u32 a, %%clock;\nW:\nmov.u32 b, %%clock;\nsub.u32 b, b, a;\nsetp.lt.s32 p, b, %0;\n@p bra.uni W;\n}" ::"r"(clks) : "memory");
}
__device__ __forceinline__ void red_bf16x8(uint32_t* p, uint32_t a, uint32_t b, uint32_t c, uint32_t d) {
  asm volatile("red.relaxed.gpu.global.add.noftz.v4.bf16x2 [%0], {%1,%2,%3,%4};" ::"l"(p), "r"(a), "r"(b), "r"(c), "r"(d) : "memory");
}
__device__ __forceinline__ void red_bf16x4(uint32_t* p, uint32_t a, uint32_t b) {
  asm volatile("red.relaxed.gpu.global.add.noftz.v2.bf16x2 [%0], {%1,%2};" ::"l"(p), "r"(a), "r"(b) : "memory");
}
constexpr int SPIN_MAX = 1 << 20;
__device__ __forceinline__ uint32_t ld_acq(const void* p) { uint32_t v; asm volatile("ld.acquire.gpu.global.b32 %0, [%1];" : "=r"(v) : "l"(p) : "memory"); return v; }
template <bool ACQ = false> __device__ __forceinline__ void wait_cnt(const unsigned* p, unsigned target) {
  int it = 0;
  while (any((int)((ACQ ? ld_acq(p) : ld_rlx(p)) - target) < 0) && ++it < SPIN_MAX) {}
}
__device__ __forceinline__ uint32_t pack_bf16(float lo, float hi) { uint32_t r; asm("cvt.rn.bf16x2.f32 %0, %1, %2;" : "=r"(r) : "f"(hi), "f"(lo)); return r; }
__device__ __forceinline__ float bf_lo(uint32_t v) { return __uint_as_float(v << 16); }
__device__ __forceinline__ float bf_hi(uint32_t v) { return __uint_as_float(v & 0xffff0000u); }
__device__ __forceinline__ uint32_t hadd2(uint32_t a, uint32_t b) { uint32_t r; asm("add.rn.bf16x2 %0, %1, %2;" : "=r"(r) : "r"(a), "r"(b)); return r; }
__device__ __forceinline__ uint32_t hmul2(uint32_t a, uint32_t b) { uint32_t r; asm("mul.rn.bf16x2 %0, %1, %2;" : "=r"(r) : "r"(a), "r"(b)); return r; }
__device__ __forceinline__ uint32_t hfma2(uint32_t a, uint32_t b, uint32_t c) { uint32_t r; asm("fma.rn.bf16x2 %0, %1, %2, %3;" : "=r"(r) : "r"(a), "r"(b), "r"(c)); return r; }
__device__ __forceinline__ float rbf(float x) { uint32_t r; asm("cvt.rn.bf16x2.f32 %0, %1, %2;" : "=r"(r) : "f"(x), "f"(0.0f)); return __uint_as_float(r); }
__device__ __forceinline__ void stmatrix4(uint32_t a, uint32_t r0, uint32_t r1, uint32_t r2, uint32_t r3) {
  asm volatile("stmatrix.sync.aligned.m8n8.x4.shared.b16 [%0], {%1,%2,%3,%4};" ::"r"(a), "r"(r0), "r"(r1), "r"(r2), "r"(r3) : "memory");
}
__device__ __forceinline__ void stmatrix2(uint32_t a, uint32_t r0, uint32_t r1) {
  asm volatile("stmatrix.sync.aligned.m8n8.x2.shared.b16 [%0], {%1,%2};" ::"r"(a), "r"(r0), "r"(r1) : "memory");
}
__device__ __forceinline__ uint32_t movm(uint32_t a) { uint32_t r; asm("movmatrix.sync.aligned.m8n8.trans.b16 %0, %1;" : "=r"(r) : "r"(a)); return r; }
template <bool ACC> __device__ __forceinline__ void mma16(float* d, uint32_t a0, uint32_t a1, uint32_t a2, uint32_t a3, uint32_t b0, uint32_t b1) {
  if (ACC) asm("mma.sync.aligned.m16n8k16.row.col.f32.bf16.bf16.f32 {%0,%1,%2,%3}, {%4,%5,%6,%7}, {%8,%9}, {%0,%1,%2,%3};"
               : "+f"(d[0]), "+f"(d[1]), "+f"(d[2]), "+f"(d[3]) : "r"(a0), "r"(a1), "r"(a2), "r"(a3), "r"(b0), "r"(b1));
  else asm("mma.sync.aligned.m16n8k16.row.col.f32.bf16.bf16.f32 {%0,%1,%2,%3}, {%4,%5,%6,%7}, {%8,%9}, {%10,%10,%10,%10};"
           : "=f"(d[0]), "=f"(d[1]), "=f"(d[2]), "=f"(d[3]) : "r"(a0), "r"(a1), "r"(a2), "r"(a3), "r"(b0), "r"(b1), "f"(0.f));
}
__device__ __forceinline__ uint32_t pin(uint32_t v) { uint32_t r; asm volatile("shfl.sync.bfly.b32 %0, %1, 0, 31, 0xffffffff;" : "=r"(r) : "r"(v)); return r; }
template <class T> __device__ __forceinline__ T* pin(T* p) {
  const uint64_t a = reinterpret_cast<uint64_t>(p);
  return reinterpret_cast<T*>((uint64_t)pin((uint32_t)a) | ((uint64_t)pin((uint32_t)(a >> 32)) << 32));
}
__device__ __forceinline__ uint32_t upin(uint32_t v) { return __shfl_sync(0xffffffffu, v, 0); }
template <class T> __device__ __forceinline__ T* upin(T* p) {
  const uint64_t a = reinterpret_cast<uint64_t>(p);
  return reinterpret_cast<T*>((uint64_t)upin((uint32_t)a) | ((uint64_t)upin((uint32_t)(a >> 32)) << 32));
}
__device__ __forceinline__ bool elect() {
  uint32_t p;
  asm volatile("{\n.reg .pred P;\nelect.sync _|P, 0xffffffff;\nselp.u32 %0, 1, 0, P;\n}" : "=r"(p));
  return p;
}
__device__ __forceinline__ uint32_t set_tag(uint32_t w, uint32_t tag) { uint32_t r; asm("lop3.b32 %0, %1, 0xfffffffe, %2, 0xea;" : "=r"(r) : "r"(w), "r"(tag)); return r; }
__device__ __forceinline__ uint32_t bitsel(uint32_t w, uint32_t m, uint32_t o) { uint32_t r; asm("lop3.b32 %0, %1, %2, %3, 0xe2;" : "=r"(r) : "r"(w), "r"(m), "r"(o)); return r; }
__device__ __forceinline__ uint32_t or3(uint32_t a, uint32_t b, uint32_t c) { uint32_t r; asm("lop3.b32 %0, %1, %2, %3, 0xfe;" : "=r"(r) : "r"(a), "r"(b), "r"(c)); return r; }
__device__ __forceinline__ uint32_t diff2(uint32_t a, uint32_t b, uint32_t tag) { uint32_t r; asm("lop3.b32 %0, %1, %2, %3, 0x7e;" : "=r"(r) : "r"(a), "r"(b), "r"(tag)); return r; }
__device__ __forceinline__ float2 cmul(float2 a, float2 b) { return make_float2(a.x * b.x - a.y * b.y, a.x * b.y + a.y * b.x); }

template<int TB> __device__ __forceinline__ void wgmma_ss_160_0(float (&d)[96], uint32_t al, uint32_t ah, uint32_t bl, uint32_t bh) {
  asm volatile("{\n.reg .b64 da, db;\nmov.b64 da, {%80, %81};\nmov.b64 db, {%82, %83};\n"
    "wgmma.mma_async.sync.aligned.m64n160k16.f32.bf16.bf16 {%0,%1,%2,%3,%4,%5,%6,%7,%8,%9,%10,%11,%12,%13,%14,%15,%16,%17,%18,%19,%20,%21,%22,%23,%24,%25,%26,%27,%28,%29,%30,%31,%32,%33,%34,%35,%36,%37,%38,%39,%40,%41,%42,%43,%44,%45,%46,%47,%48,%49,%50,%51,%52,%53,%54,%55,%56,%57,%58,%59,%60,%61,%62,%63,%64,%65,%66,%67,%68,%69,%70,%71,%72,%73,%74,%75,%76,%77,%78,%79}, da, db, 1, 1, 1, 1, %84;\n}\n"
    : "+f"(d[0]),"+f"(d[1]),"+f"(d[2]),"+f"(d[3]),"+f"(d[4]),"+f"(d[5]),"+f"(d[6]),"+f"(d[7]),"+f"(d[8]),"+f"(d[9]),"+f"(d[10]),"+f"(d[11]),"+f"(d[12]),"+f"(d[13]),"+f"(d[14]),"+f"(d[15]),"+f"(d[16]),"+f"(d[17]),"+f"(d[18]),"+f"(d[19]),"+f"(d[20]),"+f"(d[21]),"+f"(d[22]),"+f"(d[23]),"+f"(d[24]),"+f"(d[25]),"+f"(d[26]),"+f"(d[27]),"+f"(d[28]),"+f"(d[29]),"+f"(d[30]),"+f"(d[31]),"+f"(d[32]),"+f"(d[33]),"+f"(d[34]),"+f"(d[35]),"+f"(d[36]),"+f"(d[37]),"+f"(d[38]),"+f"(d[39]),"+f"(d[40]),"+f"(d[41]),"+f"(d[42]),"+f"(d[43]),"+f"(d[44]),"+f"(d[45]),"+f"(d[46]),"+f"(d[47]),"+f"(d[48]),"+f"(d[49]),"+f"(d[50]),"+f"(d[51]),"+f"(d[52]),"+f"(d[53]),"+f"(d[54]),"+f"(d[55]),"+f"(d[56]),"+f"(d[57]),"+f"(d[58]),"+f"(d[59]),"+f"(d[60]),"+f"(d[61]),"+f"(d[62]),"+f"(d[63]),"+f"(d[64]),"+f"(d[65]),"+f"(d[66]),"+f"(d[67]),"+f"(d[68]),"+f"(d[69]),"+f"(d[70]),"+f"(d[71]),"+f"(d[72]),"+f"(d[73]),"+f"(d[74]),"+f"(d[75]),"+f"(d[76]),"+f"(d[77]),"+f"(d[78]),"+f"(d[79])
    : "r"(al), "r"(ah), "r"(bl), "r"(bh), "n"(TB));
}
template<int TB> __device__ __forceinline__ void wgmma_ss_144_0(float (&d)[96], uint32_t al, uint32_t ah, uint32_t bl, uint32_t bh) {
  asm volatile("{\n.reg .b64 da, db;\nmov.b64 da, {%72, %73};\nmov.b64 db, {%74, %75};\n"
    "wgmma.mma_async.sync.aligned.m64n144k16.f32.bf16.bf16 {%0,%1,%2,%3,%4,%5,%6,%7,%8,%9,%10,%11,%12,%13,%14,%15,%16,%17,%18,%19,%20,%21,%22,%23,%24,%25,%26,%27,%28,%29,%30,%31,%32,%33,%34,%35,%36,%37,%38,%39,%40,%41,%42,%43,%44,%45,%46,%47,%48,%49,%50,%51,%52,%53,%54,%55,%56,%57,%58,%59,%60,%61,%62,%63,%64,%65,%66,%67,%68,%69,%70,%71}, da, db, 1, 1, 1, 1, %76;\n}\n"
    : "+f"(d[0]),"+f"(d[1]),"+f"(d[2]),"+f"(d[3]),"+f"(d[4]),"+f"(d[5]),"+f"(d[6]),"+f"(d[7]),"+f"(d[8]),"+f"(d[9]),"+f"(d[10]),"+f"(d[11]),"+f"(d[12]),"+f"(d[13]),"+f"(d[14]),"+f"(d[15]),"+f"(d[16]),"+f"(d[17]),"+f"(d[18]),"+f"(d[19]),"+f"(d[20]),"+f"(d[21]),"+f"(d[22]),"+f"(d[23]),"+f"(d[24]),"+f"(d[25]),"+f"(d[26]),"+f"(d[27]),"+f"(d[28]),"+f"(d[29]),"+f"(d[30]),"+f"(d[31]),"+f"(d[32]),"+f"(d[33]),"+f"(d[34]),"+f"(d[35]),"+f"(d[36]),"+f"(d[37]),"+f"(d[38]),"+f"(d[39]),"+f"(d[40]),"+f"(d[41]),"+f"(d[42]),"+f"(d[43]),"+f"(d[44]),"+f"(d[45]),"+f"(d[46]),"+f"(d[47]),"+f"(d[48]),"+f"(d[49]),"+f"(d[50]),"+f"(d[51]),"+f"(d[52]),"+f"(d[53]),"+f"(d[54]),"+f"(d[55]),"+f"(d[56]),"+f"(d[57]),"+f"(d[58]),"+f"(d[59]),"+f"(d[60]),"+f"(d[61]),"+f"(d[62]),"+f"(d[63]),"+f"(d[64]),"+f"(d[65]),"+f"(d[66]),"+f"(d[67]),"+f"(d[68]),"+f"(d[69]),"+f"(d[70]),"+f"(d[71])
    : "r"(al), "r"(ah), "r"(bl), "r"(bh), "n"(TB));
}
template<int TB> __device__ __forceinline__ void wgmma_ss_96_0(float (&d)[96], uint32_t al, uint32_t ah, uint32_t bl, uint32_t bh) {
  asm volatile("{\n.reg .b64 da, db;\nmov.b64 da, {%48, %49};\nmov.b64 db, {%50, %51};\n"
    "wgmma.mma_async.sync.aligned.m64n96k16.f32.bf16.bf16 {%0,%1,%2,%3,%4,%5,%6,%7,%8,%9,%10,%11,%12,%13,%14,%15,%16,%17,%18,%19,%20,%21,%22,%23,%24,%25,%26,%27,%28,%29,%30,%31,%32,%33,%34,%35,%36,%37,%38,%39,%40,%41,%42,%43,%44,%45,%46,%47}, da, db, 1, 1, 1, 1, %52;\n}\n"
    : "+f"(d[0]),"+f"(d[1]),"+f"(d[2]),"+f"(d[3]),"+f"(d[4]),"+f"(d[5]),"+f"(d[6]),"+f"(d[7]),"+f"(d[8]),"+f"(d[9]),"+f"(d[10]),"+f"(d[11]),"+f"(d[12]),"+f"(d[13]),"+f"(d[14]),"+f"(d[15]),"+f"(d[16]),"+f"(d[17]),"+f"(d[18]),"+f"(d[19]),"+f"(d[20]),"+f"(d[21]),"+f"(d[22]),"+f"(d[23]),"+f"(d[24]),"+f"(d[25]),"+f"(d[26]),"+f"(d[27]),"+f"(d[28]),"+f"(d[29]),"+f"(d[30]),"+f"(d[31]),"+f"(d[32]),"+f"(d[33]),"+f"(d[34]),"+f"(d[35]),"+f"(d[36]),"+f"(d[37]),"+f"(d[38]),"+f"(d[39]),"+f"(d[40]),"+f"(d[41]),"+f"(d[42]),"+f"(d[43]),"+f"(d[44]),"+f"(d[45]),"+f"(d[46]),"+f"(d[47])
    : "r"(al), "r"(ah), "r"(bl), "r"(bh), "n"(TB));
}
template<int TB> __device__ __forceinline__ void wgmma_ss_96_48(float (&d)[96], uint32_t al, uint32_t ah, uint32_t bl, uint32_t bh) {
  asm volatile("{\n.reg .b64 da, db;\nmov.b64 da, {%48, %49};\nmov.b64 db, {%50, %51};\n"
    "wgmma.mma_async.sync.aligned.m64n96k16.f32.bf16.bf16 {%0,%1,%2,%3,%4,%5,%6,%7,%8,%9,%10,%11,%12,%13,%14,%15,%16,%17,%18,%19,%20,%21,%22,%23,%24,%25,%26,%27,%28,%29,%30,%31,%32,%33,%34,%35,%36,%37,%38,%39,%40,%41,%42,%43,%44,%45,%46,%47}, da, db, 1, 1, 1, 1, %52;\n}\n"
    : "+f"(d[48]),"+f"(d[49]),"+f"(d[50]),"+f"(d[51]),"+f"(d[52]),"+f"(d[53]),"+f"(d[54]),"+f"(d[55]),"+f"(d[56]),"+f"(d[57]),"+f"(d[58]),"+f"(d[59]),"+f"(d[60]),"+f"(d[61]),"+f"(d[62]),"+f"(d[63]),"+f"(d[64]),"+f"(d[65]),"+f"(d[66]),"+f"(d[67]),"+f"(d[68]),"+f"(d[69]),"+f"(d[70]),"+f"(d[71]),"+f"(d[72]),"+f"(d[73]),"+f"(d[74]),"+f"(d[75]),"+f"(d[76]),"+f"(d[77]),"+f"(d[78]),"+f"(d[79]),"+f"(d[80]),"+f"(d[81]),"+f"(d[82]),"+f"(d[83]),"+f"(d[84]),"+f"(d[85]),"+f"(d[86]),"+f"(d[87]),"+f"(d[88]),"+f"(d[89]),"+f"(d[90]),"+f"(d[91]),"+f"(d[92]),"+f"(d[93]),"+f"(d[94]),"+f"(d[95])
    : "r"(al), "r"(ah), "r"(bl), "r"(bh), "n"(TB));
}
__device__ __forceinline__ void wgmma_rs_72(float (&d)[36], uint32_t a0, uint32_t a1, uint32_t a2, uint32_t a3, uint32_t bl, uint32_t bh, int sd) {
  asm volatile("{\n.reg .pred p;\n.reg .b64 db;\nsetp.ne.b32 p, %42, 0;\nmov.b64 db, {%40, %41};\n"
    "wgmma.mma_async.sync.aligned.m64n72k16.f32.bf16.bf16 {%0,%1,%2,%3,%4,%5,%6,%7,%8,%9,%10,%11,%12,%13,%14,%15,%16,%17,%18,%19,%20,%21,%22,%23,%24,%25,%26,%27,%28,%29,%30,%31,%32,%33,%34,%35}, {%36,%37,%38,%39}, db, p, 1, 1, 1;\n}\n"
    : "+f"(d[0]),"+f"(d[1]),"+f"(d[2]),"+f"(d[3]),"+f"(d[4]),"+f"(d[5]),"+f"(d[6]),"+f"(d[7]),"+f"(d[8]),"+f"(d[9]),"+f"(d[10]),"+f"(d[11]),"+f"(d[12]),"+f"(d[13]),"+f"(d[14]),"+f"(d[15]),"+f"(d[16]),"+f"(d[17]),"+f"(d[18]),"+f"(d[19]),"+f"(d[20]),"+f"(d[21]),"+f"(d[22]),"+f"(d[23]),"+f"(d[24]),"+f"(d[25]),"+f"(d[26]),"+f"(d[27]),"+f"(d[28]),"+f"(d[29]),"+f"(d[30]),"+f"(d[31]),"+f"(d[32]),"+f"(d[33]),"+f"(d[34]),"+f"(d[35])
    : "r"(a0), "r"(a1), "r"(a2), "r"(a3), "r"(bl), "r"(bh), "r"(sd));
}
__device__ __forceinline__ void wgmma_rs_48(float (&d)[24], uint32_t a0, uint32_t a1, uint32_t a2, uint32_t a3, uint32_t bl, uint32_t bh, int sd) {
  asm volatile("{\n.reg .pred p;\n.reg .b64 db;\nsetp.ne.b32 p, %30, 0;\nmov.b64 db, {%28, %29};\n"
    "wgmma.mma_async.sync.aligned.m64n48k16.f32.bf16.bf16 {%0,%1,%2,%3,%4,%5,%6,%7,%8,%9,%10,%11,%12,%13,%14,%15,%16,%17,%18,%19,%20,%21,%22,%23}, {%24,%25,%26,%27}, db, p, 1, 1, 1;\n}\n"
    : "+f"(d[0]),"+f"(d[1]),"+f"(d[2]),"+f"(d[3]),"+f"(d[4]),"+f"(d[5]),"+f"(d[6]),"+f"(d[7]),"+f"(d[8]),"+f"(d[9]),"+f"(d[10]),"+f"(d[11]),"+f"(d[12]),"+f"(d[13]),"+f"(d[14]),"+f"(d[15]),"+f"(d[16]),"+f"(d[17]),"+f"(d[18]),"+f"(d[19]),"+f"(d[20]),"+f"(d[21]),"+f"(d[22]),"+f"(d[23])
    : "r"(a0), "r"(a1), "r"(a2), "r"(a3), "r"(bl), "r"(bh), "r"(sd));
}
template<int N,int OFF,int TB> __device__ __forceinline__ void wgmma_ss(float (&d)[96], uint32_t al, uint32_t ah, uint32_t bl, uint32_t bh) {
  if constexpr (N==160 && OFF==0) wgmma_ss_160_0<TB>(d, al, ah, bl, bh);
  else if constexpr (N==144 && OFF==0) wgmma_ss_144_0<TB>(d, al, ah, bl, bh);
  else if constexpr (N==96 && OFF==0) wgmma_ss_96_0<TB>(d, al, ah, bl, bh);
  else if constexpr (N==96 && OFF==48) wgmma_ss_96_48<TB>(d, al, ah, bl, bh);
}

__device__ __forceinline__ void dft3(float2& a, float2& b, float2& c) {
  const float s = 0.86602540378443864676f;
  float2 t = make_float2(b.x + c.x, b.y + c.y), d = make_float2(b.x - c.x, b.y - c.y);
  float2 m = make_float2(fmaf(-0.5f, t.x, a.x), fmaf(-0.5f, t.y, a.y));
  a = make_float2(a.x + t.x, a.y + t.y);
  b = make_float2(fmaf(s, d.y, m.x), fmaf(-s, d.x, m.y));
  c = make_float2(fmaf(-s, d.y, m.x), fmaf(s, d.x, m.y));
}
__device__ __forceinline__ void dft9(float2 (&x)[9]) {
  const float2 w1 = make_float2(0.76604444311897803520f, -0.64278760968653932632f);
  const float2 w2 = make_float2(0.17364817766693034885f, -0.98480775301220805937f);
  const float2 w4 = make_float2(-0.93969262078590838405f, -0.34202014332566873304f);
  dft3(x[0], x[3], x[6]); dft3(x[1], x[4], x[7]); dft3(x[2], x[5], x[8]);
  x[4] = cmul(x[4], w1); x[7] = cmul(x[7], w2); x[5] = cmul(x[5], w2); x[8] = cmul(x[8], w4);
  dft3(x[0], x[1], x[2]); dft3(x[3], x[4], x[5]); dft3(x[6], x[7], x[8]);
  float2 t;
  t = x[1]; x[1] = x[3]; x[3] = t;
  t = x[2]; x[2] = x[6]; x[6] = t;
  t = x[5]; x[5] = x[7]; x[7] = t;
}

__device__ __forceinline__ uint32_t* mod_ptr(Scratch* sc, int u, int t128) {
  const int i = t128 & 15;
  return u < 72 ? sc->moda + (t128 >> 4) * (2 * D_) + 16 * u + 2 * (i & 7) + (i >> 3) : sc->mod + 16 * (u - 72) + i;
}
__device__ __forceinline__ void mod_unit(Scratch* sc, int u, int t128, uint32_t sw_, uint32_t bar, int ph, uint32_t rb, uint32_t tag) {
  const int w = t128 >> 5, l = t128 & 31;
  uint32_t b[18];
#pragma unroll
  for (int i = 0; i < 18; i++) b[i] = lds(red + 512 + (72 * w + 4 * i + (l & 3)) * 4);
  const uint32_t sa = pin(sw_ + (144 * w + (l & 7) + 8 * (l >> 4)) * 32 + (((l >> 3) ^ (l >> 2)) & 1) * 16);
  const uint32_t sr = pin(rb + (l >> 2) * 16 + w * 4);
  uint32_t* const dst = pin(mod_ptr(sc, u, t128));
  const int kind = u / 36;
  const float mul = __uint_as_float(pin(__float_as_uint(kind == 0 ? 16.0f : 1.0f))), add = __uint_as_float(pin(__float_as_uint(kind == 1 || kind == 4 ? 1.0f : 0.0f)));
  mbar_wait(bar, ph);
  if (t128 == 0 && u < 72) TS(10);
  float d[3][4];
#pragma unroll
  for (int i = 0; i < 9; i++) {
    uint32_t a0, a1, a2, a3;
    asm volatile("ldmatrix.sync.aligned.m8n8.x4.trans.shared.b16 {%0,%1,%2,%3}, [%4];" : "=r"(a0), "=r"(a1), "=r"(a2), "=r"(a3) : "r"(sa + i * 512) : "memory");
    if (i < 3) mma16<false>(d[i], a0, a1, a2, a3, b[2 * i], b[2 * i + 1]);
    else mma16<true>(d[i % 3], a0, a1, a2, a3, b[2 * i], b[2 * i + 1]);
  }
  if ((l & 3) == 0) { sts(sr, __float_as_uint(d[0][0] + d[1][0] + d[2][0])); sts(sr + 128, __float_as_uint(d[0][2] + d[1][2] + d[2][2])); }
  bar_sync(4, 128);
  const uint4 v = lds4(rb + (l & 15) * 16);
  const float m = rbf(fmaf(rbf((__uint_as_float(v.x) + __uint_as_float(v.y)) + (__uint_as_float(v.z) + __uint_as_float(v.w))), mul, add));
  if (u < 72 || t128 < 16) *dst = __float_as_uint(m) | tag;
}

__device__ __forceinline__ float rsq(float x) { float r; asm("rsqrt.approx.ftz.f32 %0, %1;" : "=f"(r) : "f"(x)); return r; }
__device__ __forceinline__ void ln_stats2(const float (&a)[18], const float (&b)[18], float sc, float& oa, float& ra, float& ob, float& rb) {
  float v[4] = {0.f, 0.f, 0.f, 0.f}, w[4] = {0.f, 0.f, 0.f, 0.f};
#pragma unroll
  for (int i = 0; i < 18; i += 2) {
    v[0] += a[i]; v[1] = fmaf(a[i], a[i], v[1]); v[2] += b[i]; v[3] = fmaf(b[i], b[i], v[3]);
    w[0] += a[i + 1]; w[1] = fmaf(a[i + 1], a[i + 1], w[1]); w[2] += b[i + 1]; w[3] = fmaf(b[i + 1], b[i + 1], w[3]);
  }
#pragma unroll
  for (int e = 0; e < 4; e++) v[e] += w[e];
#pragma unroll
  for (int o = 16; o; o >>= 1) {
#pragma unroll
    for (int e = 0; e < 4; e++) v[e] += __shfl_xor_sync(0xffffffffu, v[e], o);
  }
  const float ma = v[0] * (1.0f / D_), mb = v[2] * (1.0f / D_);
  ra = sc * rsq(fmaxf(fmaf(-ma, ma, v[1] * (1.0f / D_)), 0.f) + 1e-5f);
  rb = sc * rsq(fmaxf(fmaf(-mb, mb, v[3] * (1.0f / D_)), 0.f) + 1e-5f);
  oa = -ma * ra; ob = -mb * rb;
}

__device__ __forceinline__ void ln_stats1(const float (&a)[18], float sc, float& oa, float& ra) {
  float v[3] = {a[0], a[1], a[2]}, w[3] = {a[0] * a[0], a[1] * a[1], a[2] * a[2]};
#pragma unroll
  for (int i = 3; i < 18; i++) { v[i % 3] += a[i]; w[i % 3] = fmaf(a[i], a[i], w[i % 3]); }
  float s = v[0] + v[1] + v[2], q = w[0] + w[1] + w[2];
#pragma unroll
  for (int o = 16; o; o >>= 1) { s += __shfl_xor_sync(0xffffffffu, s, o); q += __shfl_xor_sync(0xffffffffu, q, o); }
  const float m = s * (1.0f / D_);
  ra = sc * rsq(fmaxf(fmaf(-m, m, q * (1.0f / D_)), 0.f) + 1e-5f);
  oa = -m * ra;
}

__device__ __forceinline__ float tmat(int c, int q, int j) {
  const int ph = q == 1 ? 1024 * j : (q >> 1) * (c + 128 * j) + 512 * (q & 1);
  return __cosf((float)(((ph + 1024) & 2047) - 1024) * (6.283185307179586f / 2048.0f));
}
__device__ __forceinline__ uint32_t line_off(int k1, int kap, int pi, int f) {
  int kd = 64 * k1 + 9 * kap;
  if (kap == 0 && k1 > 4) kd -= 288;
  if (kd >= D_) kd -= D_;
  return pi * 2400 + ((min(kd, D_ - kd) ^ f) << 3);
}

struct Ring { uint32_t st, ph; };
template <bool G2, class T> __device__ __forceinline__ void ring_next(T& st, T& ph) {
  if (++st == NST) st = 0;
  ph ^= ((G2 ? 0xDu : 0x1u) >> st) & 1;
}
__device__ __forceinline__ void arrive_if(uint32_t a, uint32_t p) {
  asm volatile("{\n.reg .pred p;\nsetp.ne.u32 p, %1, 0;\n@p mbarrier.arrive.shared::cta.b64 _, [%0];\n}" ::"r"(a), "r"(p) : "memory");
}
template <int NA> __device__ __forceinline__ void reg_fence_n(float (&d)[96]) {
#pragma unroll
  for (int i = 0; i < NA; i++) asm volatile("" : "+f"(d[i])::"memory");
}
template <int MODE>
__device__ __forceinline__ void gemm_main(float (&acc)[96], uint32_t da0, uint32_t da1, uint32_t db0, int wg, Ring& rg,
                                          bool rows, int J, uint32_t* x1p, const uint32_t (&xr)[18]) {
  constexpr int NKB = MODE == 3 ? 36 : 32;
  constexpr uint32_t HA = 0x40000040u, HB = MODE == 3 ? 0xC0000010u : 0x80000020u;
  constexpr uint32_t KA = 2048 >> 4, KB = (MODE == 3 ? 512 : 1024) >> 4;
  constexpr int NA = MODE == 3 ? 72 : MODE == 1 ? 96 : 80;
  const uint32_t t = threadIdx.x & 127;
  const uint32_t eb = full0 + 8 * NST;
  uint32_t pb = 0, rel = t == 0, prel = 0, ok = 0;
  int n = MODE == 3 ? NKB - J : X1K + 2 * wg;
#pragma unroll 1
  for (int pass = MODE == 3 ? 0 : -1;; pass++) {
#pragma unroll 1
    do {
      const uint32_t so = rg.st * ((MODE == 3 ? STAGE2 : STAGE) >> 4), cb = eb + 8 * rg.st;
      if (__builtin_expect(!ok, 0)) mbar_wait(full0 + 8 * rg.st, rg.ph);
      reg_fence_n<NA>(acc);
      if (MODE == 1 && wg) {
        wg_fence();
#pragma unroll
        for (int k = 0; k < 4; k++) wgmma_ss<96, 48, 1>(acc, da1 + so + k * KA, HA, db0 + so + k * KB, HB);
        wg_commit();
      }
      wg_fence();
#pragma unroll
      for (int k = 0; k < 4; k++) {
        if (k == 3) { ring_next<MODE == 3>(rg.st, rg.ph); ok = PEEK ? mbar_test(full0 + 8 * rg.st, rg.ph) : 0; }
        if (MODE == 0) wgmma_ss<160, 0, 1>(acc, da0 + so + k * KA, HA, db0 + so + k * KB, HB);
        else if (MODE == 3) wgmma_ss<144, 0, 1>(acc, da0 + so + k * KA, HA, db0 + so + k * KB, HB);
        else wgmma_ss<96, 0, 1>(acc, da0 + so + k * KA, HA, db0 + so + k * KB, HB);
      }
      wg_commit();
      wg_wait<1>();
      reg_fence_n<NA>(acc);
      arrive_if(pb, prel);
      pb = cb; prel = rel;
    } while (--n);
    if (pass == 2 - wg) break;
    if (MODE != 3 && pass < 0) {
      if (rows) {
#pragma unroll
        for (int i = 0; i < 9; i++) { x1p[32 * i] = xr[i]; x1p[512 * 288 + 32 * i] = xr[9 + i]; }
      }
      n = NKB - J - X1K - 2 * wg;
      continue;
    }
    n = 1;
    if (pass == 0) {
      if (MODE == 0 && J < NST) prel = rel & wg;
      if (MODE == 3) rel = 0;
      n = J - 1 + wg;
      if (!wg) continue;
      wg_wait<0>();
      arrive_if(pb, prel);
      prel = 0;
    }
    bar_sync(1, 256);
  }
  wg_wait<0>();
  reg_fence_n<NA>(acc);
  if (MODE != 3) arrive_if(pb, prel);
}

constexpr float GK1 = 2.0f * 0.7978845608028654f, GK3 = 8.0f * 0.044715f * 0.7978845608028654f;

__device__ __forceinline__ int kb2_order(int i) { const int wv = i / 6; return 6 * (i - 6 * wv) + ((0x431250 >> (4 * wv)) & 7); }

__device__ __forceinline__ int kb2_pos(int kb) { const int hf = kb >= 36, k = kb - 36 * hf, gr = k / 6; return 64 * hf + gr + 6 * ((0x154230 >> (4 * (k - 6 * gr))) & 7); }

__device__ __forceinline__ void wait_flags(const unsigned* p, int idx, unsigned target, uint32_t& ready) {
  int it = 0;
  while (!((ready >> idx) & 1) && it++ < SPIN_MAX) ready = __ballot_sync(0xffffffffu, (int)(ld_rlx(p) - target) >= 0);
}

enum { B_FULL = 0, B_EMPTY = 6, B_S4 = 12, B_S5, B_LAND, B_FLT = B_LAND + 6, B_Z1, B_Z2, B_GO, B_X, B_WM, B_NUM, B_W0 = B_NUM };

__global__ void __launch_bounds__(NTHR, 1)
fused_kernel(const Params p, const __grid_constant__ Maps maps) {
  extern __shared__ __align__(1024) uint8_t smem_raw[];
  const int bx = blockIdx.x, cta = bx < 112 || bx >= 130 ? bx : bx < 114 ? bx + 16 : bx - 2;
  const int tid = threadIdx.x, t128 = tid & 127;
  const int wp = __shfl_sync(0xffffffffu, tid >> 5, 0), wg = wp >> 2;
  const int l = tid & 31, g = l >> 2, t = l & 3;
  Scratch* const sc = p.s;
  const bool rows = cta < 128;
  const int mu = rows ? cta + 4 : cta - 128;
  const int R = mu - 12;

  uint32_t xr[18];
  uint32_t cv[3];
  const unsigned ep0 = ld_rlx(&sc->cnt[C_EP + l]);
  if (tid == 0) TS(0);
  if (wg == 2) {
#pragma unroll
    for (int i = 0; i < 3; i++) cv[i] = ld_nc(reinterpret_cast<const uint32_t*>(p.c) + min(t128 + 128 * i, 287));
    if (wp == 9 && l < 9 && rows) {
      const int h = 9 * cta + l;
      prefetch_l2(reinterpret_cast<const uint8_t*>(p.wmod) + (size_t)(h >> 1) * (12 * D_) + (h & 1) * (2 * D_), 2 * D_);
    }
    if (tid == 256 && mu < 72) {
      mbar_init(full0 + 8 * B_W0, 1);
      fence_async_smem();
      mbar_expect(full0 + 8 * B_W0, 18432);
#pragma unroll 1
      for (int i = 0; i < 3; i++) tma2d(sbase + O_P2 + i * 6144, &maps.wm, 16 * mu, 192 * i, full0 + 8 * B_W0);
    }
    __syncwarp();
#pragma unroll 1
    for (int u = mu < 72 ? mu : 72 + mu; u < 216; u += u < 72 ? 72 : NCTA) if (u < 72 || t128 < 16) *mod_ptr(sc, u, t128) = 0;
    if (wp == 11 && smem_u32(smem_raw) != sbase) __trap();
    if (wp >= 10 && elect()) {
#pragma unroll 1
      for (int i = wp - 10; i < B_NUM; i += 2) mbar_init(full0 + 8 * i, i == B_FLT ? 4 : i == B_WM ? 3 : i < B_S4 ? 2 : 1);
      fence_async_smem();
    }
    __syncwarp();
  } else if (rows) {
    const uint32_t* xs = reinterpret_cast<const uint32_t*>(p.x) + (size_t)(cta + 128 * ((wp & 3) + 8 * wg)) * 288 + l;
#pragma unroll
    for (int i = 0; i < 9; i++) { xr[i] = ld_nc(xs + 32 * i); xr[9 + i] = ld_nc(xs + 512 * 288 + 32 * i); }
  }
  CK(0);
  if (tid == 64 && cta == NCTA - 1) prefetch_l2(p.tab, sizeof(T_TAB));
  __syncwarp();
  auto tag_of = [](unsigned e) { return (e & 0x7fffu) | 0x8000u; };
  const int kap = 8 * ((wp & 3) ^ (wg & 1)) + g;
  uint32_t tb[4], sb1[3], lo[9];
#pragma unroll
  for (int i = 0; i < 4; i++) tb[i] = pin(pack_bf16(tmat(cta, 8 * (i >> 1) + g, t + 8 * (i & 1)), tmat(cta, 8 * (i >> 1) + g, t + 8 * (i & 1) + 4)));
#pragma unroll
  for (int i = 0; i < 3; i++) {
    const int d = 48 * wp + 16 * i + (l & 15);
    sb1[i] = pin(sbase + O_B1 + (l >> 4) * 9216 + (d % 9) * 1024 + (d & 63) * 16);
  }
#pragma unroll
  for (int k1 = 0; k1 < 9; k1++) lo[k1] = pin(sbase + O_Z1 + line_off(k1, kap, 4 * wg + t, cta & 3));
  const uint32_t snt = pin(sbase + O_NRM + ((l & 7) + 8 * (l >> 4)) * 1168 + (48 * wp + (l & 8)) * 2), sn = pin(sbase + O_NRM + wp * 2336 + l * 4);
  const uint32_t smask = pin(t ? 0u : 0xffff0000u);
  const uint32_t* const mp = pin(sc->moda + (cta >> 4) * (2 * D_) + 48 * wp + 2 * g);
  const uint4* const ftab = pin(p.tab + TB_F + (t128 ^ (wg << 5)));

  if (wg == 2) {
#pragma unroll
    for (int i = 0; i < 3; i++) {
      const float c0 = bf_lo(cv[i]), c1 = bf_hi(cv[i]);
      sts(red + 512 + min(t128 + 128 * i, 287) * 4, pack_bf16(__fdividef(c0, 1.0f + __expf(-c0)), __fdividef(c1, 1.0f + __expf(-c1))));
    }
    if (t128 == 0) sts(full0 + 248, ep0 + 1);
    if (wp == 9 && l < 11) asm volatile("prefetch.tensormap [%0];" ::"l"(&maps.z1 + l) : "memory");
    bar_sync(4, 128);
    if (mu < 72) {
      mod_unit(sc, mu, t128, sbase + O_P2, full0 + 8 * B_W0, 0, red, tag_of(upin(ep0) + 1));
      if (t128 == 0) TS(25);
    }
    CK(1);
  }
  const int pi = R / 15, col0 = 20 * (R - 15 * pi);
  const int xu = DF_ * pi + col0, xv = DF_ * (pi ? 16 - pi : 8) + col0;
  auto load_filter = [&](int a) {
    const int x = (a & 1) ? xv : xu;
    const bool wide = (x & 15) > 12;
    mbar_expect(full0 + 8 * B_FLT, wide ? 12288 : 8192);
    tma2d(sbase + O_RAW + a * 12288, &maps.wf[a & 2], x & ~15, 0, full0 + 8 * B_FLT);
    if (wide) tma2d(sbase + O_RAW + a * 12288 + 8192, &maps.wf[(a & 2) + 1], (x & ~15) + 32, 0, full0 + 8 * B_FLT);
  };
  uint4 af[4];
  if (rows) {
    uint2 ms[3], mc[3];
    auto load_mod = [&](uint32_t o = 0) {
#pragma unroll
      for (int i = 0; i < 3; i++) { ms[i] = ld_rlx2(mp + 2 * o + 16 * i); mc[i] = ld_rlx2(mp + 2 * o + D_ + 16 * i); }
    };
    if (wg < 2) {
      float a[18], b[18];
#pragma unroll
      for (int i = 0; i < 9; i++) { a[2 * i] = bf_lo(xr[i]); a[2 * i + 1] = bf_hi(xr[i]); b[2 * i] = bf_lo(xr[9 + i]); b[2 * i + 1] = bf_hi(xr[9 + i]); }
      float oa, ra, ob, rb;
      ln_stats2(a, b, 1.0f, oa, ra, ob, rb);
      CK(1);
      load_mod((__float_as_uint(ra) | __float_as_uint(rb)) >> 31);
#pragma unroll
      for (int i = 0; i < 9; i++) {
        sts(sn + i * 128, pack_bf16(fmaf(a[2 * i], ra, oa), fmaf(a[2 * i + 1], ra, oa)));
        sts(sn + 1168 + i * 128, pack_bf16(fmaf(b[2 * i], rb, ob), fmaf(b[2 * i + 1], rb, ob)));
      }
      CK(2);
      bar_arrive(10, NTHR);
#pragma unroll
      for (int kk = 0; kk < 4; kk++) af[kk] = ld_nc4(ftab + kk * 128);
      bar_sync(1, 256);
      if (tid == 0) TS(2);
    } else {
      bar_sync(10, NTHR);
      load_mod();
      CK(2);
      if (wp >= 10 && elect()) prefetch_l2(reinterpret_cast<const uint8_t*>(wp == 10 ? p.wr : p.wi) + cta * 9248, 9248);
      __syncwarp();
    }
    float rs[3][8];
#pragma unroll
    for (int i = 0; i < 3; i++) {
      uint32_t a0, a1, a2, a3;
      asm volatile("ldmatrix.sync.aligned.m8n8.x4.trans.shared.b16 {%0,%1,%2,%3}, [%4];" : "=r"(a0), "=r"(a1), "=r"(a2), "=r"(a3)
                   : "r"(snt + 32 * i) : "memory");
      mma16<false>(&rs[i][0], a0, a1, a2, a3, tb[0], tb[1]);
      mma16<false>(&rs[i][4], a0, a1, a2, a3, tb[2], tb[3]);
    }
    CK(3);
    const uint32_t tag16 = tag_of(upin(ep0) + 1), tag1 = tag16 & 1;
    {
      int it = 0;
#pragma unroll 1
      while (true) {
        uint32_t bad = 0;
#pragma unroll
        for (int i = 0; i < 3; i++) bad |= diff2(ms[i].x, ms[i].y, tag16) | diff2(mc[i].x, mc[i].y, tag16);
        if (!any(bad & 0xffffu) || ++it > SPIN_MAX) break;
        load_mod();
      }
      CK(4);
      if (tid == 0) TS(3);
#pragma unroll
      for (int i = 0; i < 3; i++) {
        const float c0 = bf_hi(mc[i].x), c1 = bf_hi(mc[i].y);
        const float s0 = __uint_as_float(ms[i].x & smask), s1 = __uint_as_float(ms[i].y & smask);
        stmatrix4(sb1[i], pack_bf16(fmaf(rs[i][0], c0, s0), rs[i][1] * c0), pack_bf16(fmaf(rs[i][2], c1, s1), rs[i][3] * c1),
                  pack_bf16(rs[i][4] * c0, rs[i][5] * c0), pack_bf16(rs[i][6] * c1, rs[i][7] * c1));
      }
    }
    fence_async_smem();
    CK(5);
    if (wg == 2) {
      bar_arrive(5, NTHR);
      if (R >= 0 && elect()) load_filter(wp - 8);
      __syncwarp();
      const int slot = 4 * (cta & 7) + ((cta >> 4) & 3) + 32 * (2 * (cta >> 6) + ((cta >> 3) & 1));
      const uint32_t c0 = upin(40 * slot), c1 = upin(60 * (wp & 1)), src = upin(sbase + O_Z1 + (wp & 1) * 9600);
      const CUtensorMap* mz = upin(&maps.z1);
      unsigned* hint = pin(sc->cnt + C_Z1 + 32 * (wp & 1));
      if (wp < 10) {
        bar_sync(2 + (wp & 1), 160);
        if (elect()) tma_st2d(mz, src, c0, c1);
        pause(HD1);
        if (elect()) red_add(hint, 1);
        bulk_commit_wait();
        if (tid == 256) TS(4);
        __syncwarp();
      }
    } else {
      bar_sync(5, NTHR);
      CK(6);
      float acc[36];
      const uint32_t db = (((sbase + O_B1 + wg * 9216) & 0x3FFFF) >> 4) | ((128 >> 4) << 16);
      wg_fence();
#pragma unroll
      for (int kk = 0; kk < 4; kk++) wgmma_rs_72(acc, af[kk].x, af[kk].y, af[kk].z, af[kk].w, db + kk * 16, 1024 >> 4, kk);
      wg_commit();
      wg_wait<0>();
      reg_fence(acc);
      CK(7);
      float2 za[9], zb[9];
#pragma unroll
      for (int i = 0; i < 9; i++) { za[i] = make_float2(acc[4 * i], acc[4 * i + 2]); zb[i] = make_float2(acc[4 * i + 1], acc[4 * i + 3]); }
      dft9(za); dft9(zb);
      if ((wp & 3) == wg) {
        const float sp = g ? 0.f : 1.f;
#pragma unroll
        for (int k = 1; k < 5; k++) {
          float2 a = za[k], b = za[9 - k];
          za[k] = make_float2(fmaf(sp, b.x, a.x), fmaf(-sp, b.y, a.y)); za[9 - k] = make_float2(fmaf(-sp, a.x, b.x), fmaf(sp, a.y, b.y));
          a = zb[k]; b = zb[9 - k];
          zb[k] = make_float2(fmaf(sp, b.x, a.x), fmaf(-sp, b.y, a.y)); zb[9 - k] = make_float2(fmaf(-sp, a.x, b.x), fmaf(sp, a.y, b.y));
        }
        const uint32_t w0 = set_tag(pack_bf16(za[0].y, 0.f), tag1), w1 = pack_bf16(zb[0].y, 0.f);
        asm volatile("{\n.reg .pred p;\nsetp.eq.u32 p, %3, 0;\n@p st.shared.v2.b32 [%0], {%1,%2};\n}" ::"r"(lo[0] + 288 * 8), "r"(w0), "r"(w1), "r"(g) : "memory");
        za[0].y = g ? za[0].y : 0.f; zb[0].y = g ? zb[0].y : 0.f;
      }
#pragma unroll
      for (int k1 = 0; k1 < 9; k1++) sts2(lo[k1], set_tag(pack_bf16(za[k1].x, za[k1].y), tag1), pack_bf16(zb[k1].x, zb[k1].y));
      fence_async_smem();
      CK(8);
      bar_arrive(2 + wg, 160);
      {
        const uint32_t fx = (((cta >> 4) ^ cta) & 3) << 3, dl = O_IN - O_Z1, st = sbase + O_ST + 15360 + tid * 16;
        sts4(st, (lo[0] ^ fx) + dl, (lo[1] ^ fx) + dl, (lo[2] ^ fx) + dl, (lo[3] ^ fx) + dl);
        sts4(st + 4096, (lo[4] ^ fx) + dl, (lo[5] ^ fx) + dl, (lo[6] ^ fx) + dl, (lo[7] ^ fx) + dl);
        sts4(st + 8192, (lo[8] ^ fx) + dl, (lo[0] ^ fx) + dl + (kap ? 0 : 288 * 8),
             sbase + O_B3 + wg * 1024 + (l >> 4) * 2048 + (2 * (kap & 24) + (l & 15)) * 16, 0);
      }
    }
    {
      uint32_t sy[6];
#pragma unroll
      for (int i = 0; i < 6; i++) {
        const int rr = 16 * (wp & 3) + g + 8 * (i & 1);
        sy[i] = sbase + O_Y + (t * 584 + 64 * ((3 * wg + (i >> 1) + 63 - rr) % 9) + rr) * 4;
      }
      sts4(sbase + O_ST + tid * 16, movm(tb[0]), movm(tb[2]), movm(tb[1]), movm(tb[3]));
      sts4(sbase + O_ST + 6144 + tid * 16, sy[0], sy[1], sy[2], sy[3]);
      sts2(sbase + O_ST + 12288 + tid * 8, sy[4], sy[5]);
    }
  } else {
    __syncthreads();
  }

  const unsigned ep = upin(lds(full0 + 248));
  const uint32_t tag16 = tag_of(ep), tag1 = ep & 1;
  auto load_wm = [&](int u) {
    if (wp > 8 && elect()) {
      mbar_expect(full0 + 8 * B_WM, 6144);
      tma2d(sbase + O_NRM + (wp - 9) * 6144, &maps.wm, 16 * u, 192 * (wp - 9), full0 + 8 * B_WM);
    }
    __syncwarp();
  };
  if (R >= 0) {
    const int nl = (col0 + wp < DF_) + (wg < 2 && col0 + wp + 12 < DF_);
    uint4 cf[2][4], G[4];
#pragma unroll
    for (int i = 0; i < 4; i++) {
      cf[0][i] = __ldg(p.tab + TB_P2 + i * 32 + l);
      cf[1][i] = __ldg(p.tab + TB_P2 + (pi ? i : 4 + i) * 32 + l);
      G[i] = __ldg(p.tab + TB_P2 + (8 + i) * 32 + l);
    }
    const uint32_t* zin = sc->z1 + (size_t)R * 5120;
    if (wp == 10) {
      const uint32_t* zu = upin(zin);
      if (elect()) mbar_expect(full0 + 8 * B_Z1, 20480);
      wait_cnt(sc->cnt + C_Z1 + 32 * (pi >> 2), 128 * ep - 40 * STRESS);
      if (elect()) {
        bulk_ld(sbase + O_P2, zu, 20480, full0 + 8 * B_Z1);
        TS(12);
      }
      __syncwarp();
    }
    mbar_wait(full0 + 8 * B_FLT, 0);
    CK(9);
    float wn[16], wc[16];
#pragma unroll 1
    for (int ln = nl - 1; ln >= 0; ln--) {
      const int col = col0 + wp + 12 * ln, k2 = (57 * col) & 63;
      const bool cj = k2 > 32;
      const float nr = ((col & 31) == 0 && col != 0 && col != 288 ? 0.5f : 1.0f) / ((float)S_ * D_), ni = cj ? -nr : nr;
#pragma unroll
      for (int i = 0; i < 16; i++) wn[i] = wc[i];
#pragma unroll
      for (int cl = 0; cl < 2; cl++) {
        const int v = cl ^ (cj && pi), e = ((v ? xv : xu) & 15) + wp + 12 * ln, sh = e < 32 ? 6 : 5;
        const uint32_t base = sbase + O_RAW + v * 12288 + (e < 32 ? 2 * e : 8192 - 64 + 2 * e), msk = e < 32 ? 0x30 : 0x10;
        const int dm = v ? (cj || pi ? -1 : 0) : 0;
#pragma unroll
        for (int tt = 0; tt < 4; tt++) {
          const int kc = g + 64 * (tt >> 1) + 16 * t + 8 * (tt & 1);
          uint32_t a = base + ((((cj ? -kc : kc) + dm) & 127) << sh);
          a ^= (a >> 3) & msk;
          wc[4 * tt + 2 * cl] = lds_bf(a) * nr; wc[4 * tt + 2 * cl + 1] = lds_bf(a + 24576) * ni;
        }
      }
    }
    const float al = __uint_as_float(pin((pi ? 0x3f800000u : 0u) + (l >> 5)));
    const uint32_t tagv = pin(tag1 + (l >> 5));
    CK(10);
    uint32_t off = pin(l * 160 + ((wp ^ (g & 3)) << 3));
    uint32_t offo = pin(sbase + O_P2 + 20480 + off - 64 * l), po = 3072;
    unsigned* hz2 = pin(sc->cnt + C_Z2);
    const uint32_t do2 = pin(12288 - 32 * l);
    const CUtensorMap* mz2 = upin(&maps.z2[wp == 0]);
    const uint32_t sz2 = upin(sbase + O_P2 + 20480 + (wp ? 0 : 12288)), cz2 = upin(40 * R + (wp ? 0 : 24));
    mbar_wait(full0 + 8 * B_Z1, 0);
    CK(11);
    if (tid == 0) TS(8);
    if (wg == 2) load_wm(72 + mu);
    uint2 v[4], v2[4];
    const uint32_t o2 = nl > 1 ? 96 : 0;
#pragma unroll
    for (int i = 0; i < 4; i++) { v[i] = lds2(sbase + O_P2 + off + i * 5120); v2[i] = lds2(sbase + O_P2 + off + o2 + i * 5120); }
    auto bad2 = [&]() {
      return any(or3(or3(diff2(v[0].x, v[1].x, tagv), diff2(v[2].x, v[3].x, tagv), diff2(v2[0].x, v2[1].x, tagv)), diff2(v2[2].x, v2[3].x, tagv), 0) & 1);
    };
    if (__builtin_expect(bad2() && nl, 0)) {
      FAILCNT(0);
      int it = 0;
      do {
#pragma unroll
        for (int i = 0; i < 4; i++) {
          v[i] = ld_rlx2(reinterpret_cast<const uint8_t*>(zin) + off + i * 5120);
          v2[i] = ld_rlx2(reinterpret_cast<const uint8_t*>(zin) + off + o2 + i * 5120);
        }
      } while (bad2() && ++it < SPIN_MAX);
    }
#pragma unroll 1
    for (int ln = 0; ln < nl; ln++, offo += do2, po = 2048) {
      float d[4][4];
      uint32_t A[8];
#pragma unroll
      for (int h = 0; h < 2; h++) {
        mma16<false>(d[2 * h], cf[0][0].x, cf[0][0].y, cf[0][0].z, cf[0][0].w, v[h].x, v[2 + h].x);
        mma16<false>(d[2 * h + 1], cf[1][0].x, cf[1][0].y, cf[1][0].z, cf[1][0].w, v[h].y, v[2 + h].y);
      }
      if (ln) { fence_async_smem(); bar_arrive(15, NTHR); }
#pragma unroll
      for (int h = 0; h < 2; h++)
#pragma unroll
        for (int L = 0; L < 2; L++) {
          const uint4 tw = cf[L][2 + h];
          const float* z = d[2 * h + L];
          const float2 z0 = cmul(make_float2(z[0], z[2]), make_float2(__uint_as_float(tw.x), __uint_as_float(tw.y)));
          const float2 z1 = cmul(make_float2(z[1], z[3]), make_float2(__uint_as_float(tw.z), __uint_as_float(tw.w)));
          A[4 * h + L] = pack_bf16(z0.x, z0.y); A[4 * h + 2 + L] = pack_bf16(z1.x, z1.y);
        }
#pragma unroll
      for (int tt = 0; tt < 4; tt++) {
        mma16<false>(d[tt], A[0], A[1], A[2], A[3], G[tt].x, G[tt].y);
        mma16<true>(d[tt], A[4], A[5], A[6], A[7], G[tt].z, G[tt].w);
      }
#pragma unroll
      for (int tt = 0; tt < 4; tt++) {
        const float ar = d[tt][0], aj = d[tt][1], br = d[tt][2], bj = d[tt][3];
        const float2 y1 = cmul(make_float2(fmaf(-al, bj, ar), fmaf(al, br, aj)), make_float2(wc[4 * tt], wc[4 * tt + 1]));
        const float2 y2 = cmul(make_float2(fmaf(al, ar, bj), fmaf(al, aj, -br)), make_float2(wc[4 * tt + 2], wc[4 * tt + 3]));
        A[2 * tt] = pack_bf16(fmaf(al, y2.x, y1.x), fmaf(-al, y2.y, -y1.y));
        A[2 * tt + 1] = pack_bf16(fmaf(al, y1.y, -y2.y), fmaf(al, y1.x, -y2.x));
      }
#pragma unroll
      for (int i = 0; i < 16; i++) wc[i] = wn[i];
#pragma unroll
      for (int i = 0; i < 4; i++) v[i] = v2[i];
#pragma unroll
      for (int tt = 0; tt < 4; tt++) {
        mma16<false>(d[tt], A[0], A[1], A[2], A[3], G[tt].x, G[tt].y);
        mma16<true>(d[tt], A[4], A[5], A[6], A[7], G[tt].z, G[tt].w);
      }
#pragma unroll
      for (int h = 0; h < 2; h++)
#pragma unroll
        for (int L = 0; L < 2; L++) {
          const uint4 tw = cf[L][2 + h];
          const float2 z0 = cmul(make_float2(d[2 * h][2 * L], d[2 * h][2 * L + 1]), make_float2(__uint_as_float(tw.x), __uint_as_float(tw.y)));
          const float2 z1 = cmul(make_float2(d[2 * h + 1][2 * L], d[2 * h + 1][2 * L + 1]), make_float2(__uint_as_float(tw.z), __uint_as_float(tw.w)));
          A[4 * h + 2 * L] = movm(pack_bf16(z0.x, z1.x)); A[4 * h + 2 * L + 1] = movm(pack_bf16(z0.y, z1.y));
        }
#pragma unroll
      for (int h = 0; h < 2; h++) {
        mma16<false>(d[0], cf[0][1].x, cf[0][1].y, cf[0][1].z, cf[0][1].w, A[4 * h], A[4 * h + 1]);
        mma16<false>(d[1], cf[1][1].x, cf[1][1].y, cf[1][1].z, cf[1][1].w, A[4 * h + 2], A[4 * h + 3]);
#pragma unroll
        for (int e = 0; e < 2; e++)
          sts2(offo + (2 * h + e) * po, set_tag(pack_bf16(d[0][e], d[0][2 + e]), tagv), pack_bf16(d[1][e], d[1][2 + e]));
      }
      CK(12 + ln);
    }
    if (tid == 0) TS(1);
    fence_async_smem();
    if (nl < 2 && wp != 8) bar_arrive(15, NTHR);
    if (wp) bar_arrive(6, NTHR);
    if (!(wp & 7)) {
      bar_sync(wp ? 15 : 6, NTHR);
      if (elect()) tma_st2d(mz2, sz2, cz2, 0);
      if (wp == 0 && elect()) red_add(hz2, 1);
      if (tid == 0) TS(9);
      if (wp == 0) bulk_commit_wait();
      __syncwarp();
    }
  }
  if (wg == 2) {
#pragma unroll 1
    for (int u = 72 + mu, k = 0; u < 216; u += NCTA, k ^= 1) {
      if (R < 0) { fence_async_smem(); bar_sync(4, 128); load_wm(u); }
      mod_unit(sc, u, t128, sbase + O_NRM, full0 + 8 * B_WM, k, red + 256 - 256 * k, tag16);
    }
    fence_async_smem();
    CK(13);
  }

  const int grp = bx / 11, m1 = bx - 11 * grp;
  const bool helper = (m1 & 3) == 3;
  const int f1 = 384 * grp + (helper ? 192 : 128) * (m1 >> 2);
  const int d1 = 160 * (m1 & 3), flip = m1 >= 7;
  const int a1bytes = helper ? 24576 : 16384;
  auto load_a1 = [&](int st, int kb) {
    mbar_expect(full0 + 8 * st, a1bytes);
    tma4d_ef(sbase + st * STAGE, helper ? &maps.w1b : &maps.w1a, 4 * (kb >> 3), 16 * (kb & 7), f1 >> 6, full0 + 8 * st);
  };

  uint32_t bia[4];
  if (wg < 2) {
    const int fa = f1 + (helper ? 128 : 64) * (wg ^ flip) + 16 * (wp & 3) + g, fb = helper ? f1 + 64 + 16 * (wp & 3) + g : fa;
#pragma unroll
    for (int i = 0; i < 4; i++) asm volatile("ld.global.nc.u16 %0, [%1];" : "=r"(bia[i]) : "l"(p.b1 + (i < 2 ? fa : fb) + 8 * (i & 1)) : "memory");
  }
  if (rows) {
#pragma unroll
    for (int kk = 0; kk < 4; kk++) af[kk] = __ldg(p.tab + TB_E + kk * 128 + t128);
    const uint4 c0 = lds4(sbase + O_ST + tid * 16), c1 = lds4(sbase + O_ST + 6144 + tid * 16);
    const uint2 c2 = lds2(sbase + O_ST + 12288 + tid * 8);
    const uint32_t tc[4] = {c0.x, c0.y, c0.z, c0.w}, sy[6] = {c1.x, c1.y, c1.z, c1.w, c2.x, c2.y};
    const uint32_t l8 = pin(8 * l), syl = pin(sbase + O_Y + wp * 2336 + 8 * l);
    uint32_t sh3[3], ham[3];
#pragma unroll
    for (int k = 0; k < 3; k++) {
      const int pos = k && (l >> 4) == k - 1 ? 2 * (l & 6) + ((l >> 2) & 2) + (l & 1) : l & 15;
      const int sw = 2 * cta + ((wp >> 1) & 1), ph = pos ^ ((sw & 3) << 2);
      sh3[k] = pin((l >> 4) * 256 + (wp & 3) * 64 + ph * 4);
      ham[k] = pin(((ph ^ sw) & 7) == 0 ? ~1u : ~0u);
    }
    unsigned* const hh3 = upin(sc->cnt + C_H3 + (cta >> 4));
    uint8_t* const h3g = pin(sc->h3 + (cta >> 4) * (18 * 4096) + (cta & 15) * 256 + (l >> 4) * 3840);
    const int slot = 4 * (cta >> 4) + ((cta >> 1) & 3) + 32 * (2 * ((cta >> 3) & 1) + (cta & 1));
    const uint32_t* zin = sc->z2 + (size_t)slot * 4800;
    if (wg == 2) {
      {
        uint4 v[4];
        const int i3 = min(t128 + 384, 431);
        int it = 0;
        while (true) {
          uint32_t bad = 0;
#pragma unroll
          for (int k = 0; k < 4; k++) v[k] = ld_rlx4(sc->mod + 4 * (k < 3 ? t128 + 128 * k : i3));
#pragma unroll
          for (int k = 0; k < 4; k++) {
            v[k].x ^= tag16; v[k].y ^= tag16; v[k].z ^= tag16; v[k].w ^= tag16;
            bad |= v[k].x | v[k].y | v[k].z | v[k].w;
          }
          if (!any(bad & 0xffffu) || ++it > SPIN_MAX) break;
        }
#pragma unroll
        for (int k = 0; k < 4; k++) sts4(sbase + O_MOD + 16 * (k < 3 ? t128 + 128 * k : i3), v[k].x, v[k].y, v[k].z, v[k].w);
      }
      CK(14);
      bulk_commit_wait();
      bar_sync(10, NTHR);
      mbar_wait(full0 + 8 * B_Z2, 0);
      if (elect()) {
        load_a1(wp - 8, wp - 8);
      }
      __syncwarp();
    } else {
      const uint4 e0 = lds4(sbase + O_ST + 15360 + tid * 16), e1 = lds4(sbase + O_ST + 19456 + tid * 16), e2 = lds4(sbase + O_ST + 23552 + tid * 16);
      const uint32_t li[9] = {e0.x, e0.y, e0.z, e0.w, e1.x, e1.y, e1.z, e1.w, e2.x}, lx = e2.y, sb3 = e2.z;
      bar_arrive(10, NTHR);
      CK(14);
      if (wp == 1) {
        const uint32_t* zu = upin(zin);
        if (elect()) mbar_expect(full0 + 8 * B_Z2, 19200);
        wait_cnt(sc->cnt + C_Z2, 120 * ep - 40 * STRESS);
        if (elect()) {
          bulk_ld(sbase + O_IN, zu, 19200, full0 + 8 * B_Z2);
          TS(14);
        }
        __syncwarp();
      }
      mbar_wait(full0 + 8 * B_Z2, 0);
      CK(15);
      if (tid == 0) TS(11);
      uint2 v[10];
#pragma unroll
      for (int k1 = 0; k1 < 10; k1++) v[k1] = lds2(k1 < 9 ? li[k1] : lx);
      auto bad3 = [&]() {
        return any(or3(or3(diff2(v[0].x, v[1].x, tag1), diff2(v[2].x, v[3].x, tag1), diff2(v[4].x, v[5].x, tag1)), diff2(v[6].x, v[7].x, tag1), diff2(v[8].x, v[9].x, tag1)) & 1);
      };
      if (__builtin_expect(bad3(), 0)) {
        FAILCNT(1);
        int it = 0;
        do {
#pragma unroll
          for (int k1 = 0; k1 < 10; k1++) v[k1] = ld_rlx2(reinterpret_cast<const uint8_t*>(zin) + ((k1 < 9 ? li[k1] : lx) - (sbase + O_IN)));
        } while (bad3() && ++it < SPIN_MAX);
      }
      float2 za[9], zb[9];
#pragma unroll
      for (int i = 0; i < 9; i++) { za[i] = make_float2(bf_lo(v[i].x), bf_hi(v[i].x)); zb[i] = make_float2(bf_lo(v[i].y), bf_hi(v[i].y)); }
      if ((wp & 3) == wg) {
        const float sp = g ? 0.f : 1.f;
#pragma unroll
        for (int k = 1; k < 5; k++) {
          float2 a = za[k], b = za[9 - k];
          za[k] = make_float2(fmaf(-sp, b.x, a.x), fmaf(sp, b.y, a.y)); za[9 - k] = make_float2(fmaf(sp, a.x, b.x), fmaf(-sp, a.y, b.y));
          a = zb[k]; b = zb[9 - k];
          zb[k] = make_float2(fmaf(-sp, b.x, a.x), fmaf(sp, b.y, a.y)); zb[9 - k] = make_float2(fmaf(sp, a.x, b.x), fmaf(-sp, a.y, b.y));
        }
        za[0].y = g ? za[0].y : bf_lo(v[9].x); zb[0].y = g ? zb[0].y : bf_lo(v[9].y);
      }
      dft9(za); dft9(zb);
#pragma unroll
      for (int n = 0; n < 8; n += 2) {
        const int i0 = (9 - n) % 9, i1 = 8 - n;
        stmatrix4(sb3 + n * 2048, pack_bf16(za[i0].x, zb[i0].x), pack_bf16(za[i0].y, zb[i0].y), pack_bf16(za[i1].x, zb[i1].x), pack_bf16(za[i1].y, zb[i1].y));
      }
      stmatrix2(sb3 + 8 * 2048, pack_bf16(za[1].x, zb[1].x), pack_bf16(za[1].y, zb[1].y));
      fence_async_smem();
    }
    CK(16);
    __syncthreads();
    CK(17);
    float acc[24];
    const uint32_t db = (((sbase + O_B3 + wg * 6144) & 0x3FFFF) >> 4) | ((128 >> 4) << 16);
    wg_fence();
#pragma unroll
    for (int kk = 0; kk < 4; kk++) wgmma_rs_48(acc, af[kk].x, af[kk].y, af[kk].z, af[kk].w, db + kk * 16, 1024 >> 4, kk);
    wg_commit();
    uint32_t ga[9];
    if (wg < 2) {
#pragma unroll
      for (int i = 0; i < 9; i++) { const uint2 v = lds2(l8 + sbase + O_MOD + 256 * i); ga[i] = __byte_perm(v.x, v.y, 0x7632); }
    }
    wg_wait<0>();
    reg_fence(acc);
    CK(18);
#pragma unroll
    for (int i = 0; i < 3; i++) {
      const float* a = &acc[8 * i];
      const uint32_t a0 = pack_bf16(a[0], a[1]), a1 = pack_bf16(a[2], a[3]), a2 = pack_bf16(a[4], a[5]), a3 = pack_bf16(a[6], a[7]);
#pragma unroll
      for (int jh = 0; jh < 2; jh++) {
        float y[4];
        mma16<false>(y, a0, a1, a2, a3, tc[2 * jh], tc[2 * jh + 1]);
        sts(sy[2 * i] + jh * (4 * 584 * 4), pack_bf16(y[0], y[1]));
        sts(sy[2 * i + 1] + jh * (4 * 584 * 4), pack_bf16(y[2], y[3]));
      }
    }
    CK(19);
    if (wg == 2) bar_arrive(7, NTHR); else bar_sync(7, NTHR);
    if (wg) bar_sync(15, NTHR);
    if (wg < 2) {
      CK(20);
      uint2 y[9], sh[9], sw[9];
#pragma unroll
      for (int i = 0; i < 9; i++) y[i] = lds2(syl + 256 * i);
      uint32_t sel = 0x5410, sto = sbase + O_B3 + wg * 9216;
#pragma unroll 1
      for (int e = 0; e < 2; e++, sel = 0x7632, sto += 4608) {
        float a[18];
#pragma unroll
        for (int i = 0; i < 9; i++) {
          const uint32_t x1 = hfma2(ga[i], __byte_perm(y[i].x, y[i].y, sel), xr[i]);
          xr[i] = xr[9 + i]; xr[9 + i] = x1;
          a[2 * i] = bf_lo(x1); a[2 * i + 1] = bf_hi(x1);
        }
#pragma unroll
        for (int i = 0; i < 9; i++) { lds2_if(!e, sh[i], l8 + sbase + O_MOD + 4 * D_ + 256 * i); lds2_if(!e, sw[i], l8 + sbase + O_MOD + 8 * D_ + 256 * i); }
        float oa, ra;
        ln_stats1(a, 1.0f, oa, ra);
#pragma unroll
        for (int i = 0; i < 9; i++) {
          a[2 * i] = fmaf(fmaf(a[2 * i], ra, oa), __uint_as_float(sw[i].x), __uint_as_float(sh[i].x));
          a[2 * i + 1] = fmaf(fmaf(a[2 * i + 1], ra, oa), __uint_as_float(sw[i].y), __uint_as_float(sh[i].y));
        }
        ln_stats1(a, 0.5f, oa, ra);
        uint32_t hv[9];
#pragma unroll
        for (int i = 0; i < 9; i++) hv[i] = bitsel(pack_bf16(fmaf(a[2 * i], ra, oa), fmaf(a[2 * i + 1], ra, oa)), ham[i == 2 ? 1 : i == 6 ? 2 : 0], tag1);
        if (!(wg | e)) {
          if (elect()) red_add(hh3, 1);
#pragma unroll
          for (int i = 0; i < 9; i++) asm volatile("st.global.b32 [%0], %1;" ::"l"(h3g + sh3[i == 2 ? 1 : i == 6 ? 2 : 0] + i * 8192), "r"(hv[i]) : "memory");
          bar_arrive(15, NTHR);
          if (tid == 0) TS(13);
        } else {
#pragma unroll
          for (int i = 0; i < 9; i++) sts(sto + sh3[i == 2 ? 1 : i == 6 ? 2 : 0] + i * 512, hv[i]);
        }
        if (!e) bar_arrive(8, 288);
        CK(21 + e);
      }
      fence_async_smem();
      bar_arrive(9, 288);
      CK(23);
    }
  }

  const bool g2 = rows;
  const int z2 = cta, r = z2 >> 6;
  const int s2 = 128 * ((z2 >> 2) & 15), d2 = 144 * (z2 & 3);
  constexpr int ST0 = 32 % NST;
  const bool first = helper || m1 < W0N;

  if (wg == 2) {
    asm volatile("setmaxnreg.dec.sync.aligned.u32 40;");
    auto load_b = [&](bool second, int i, int st) {
      const uint32_t lb = full0 + 8 * (B_LAND + st), bytes = second ? 18432 : STAGE - a1bytes;
      mbar_expect(lb, bytes);
      bulk_ld(sbase + (second ? st * STAGE2 + 16384 : st * STAGE + a1bytes),
              second ? sc->u + ((size_t)(36 * r + kb2_order(i)) * D_ + d2) * 128 : sc->h3 + ((size_t)(i * 18 + (d1 >> 5)) << 12), bytes, lb);
    };
    if (wp == 8) {
      int st = rows ? 4 : 0, ph = 1;
#pragma unroll 1
      for (int kb = st; kb < 32; kb++) {
        if (rows && (kb >> 1) == 2) mbar_wait(full0 + 8 * (B_S4 - 4 + kb), 0);
        mbar_wait(empty0 + 8 * st, ph);
        if (elect()) {
          load_a1(st, kb);
        }
        __syncwarp();
        ring_next<false>(st, ph);
      }
      if (g2) {
        st++;
#pragma unroll 1
        for (int i = 0; i < 36; i++) {
          if (i == HOLDA) mbar_wait(full0 + 8 * B_GO, 0);
          mbar_wait(empty0 + 8 * st, ph);
          if (elect()) {
            mbar_expect(full0 + 8 * st, 16384);
            tma3d_ef(sbase + st * STAGE2, &maps.w2, 64 * (36 * r + kb2_order(i)), s2 >> 6, full0 + 8 * st);
          }
          __syncwarp();
          ring_next<true>(st, ph);
        }
      }
    } else if (wp >= 10) {
      const int sw = wp - 10;
      if (sw) {
        if (rows) {
          bar_sync(8, 288);
          mbar_wait(full0 + 8 * H3W, 0);
          if (elect()) mbar_arrive(full0 + 8 * B_S4);
          bar_sync(9, 288);
          if (elect()) tma_st3d(&maps.h3, sbase + O_B3 + 4608, 64 * (cta & 15), 18 * (cta >> 4), 1);
          bulk_commit_wait();
          if (elect()) {
            red_add(sc->cnt + C_H3 + (cta >> 4) + 8, 4);
            mbar_arrive(full0 + 8 * B_S5);
            TS(24);
            asm volatile("fence.acq_rel.gpu;" ::: "memory");
            red_add(&sc->cnt[C_X + 64], 1);
          }
          __syncwarp();
        }
        if (g2) {
          uint2 v[3];
          int it = 0;
          do {
#pragma unroll
            for (int i = 0; i < 3; i++) v[i] = ld_rlx2(sc->mod + 3 * D_ + d2 + 2 * min(l + 32 * i, 71));
          } while (any(or3(diff2(v[0].x, v[0].y, tag16), diff2(v[1].x, v[1].y, tag16), diff2(v[2].x, v[2].y, tag16)) & 0xffffu) && ++it < SPIN_MAX);
#pragma unroll
          for (int i = 0; i < 3; i++) sts(sbase + O_GB + 4 * min(l + 32 * i, 71), __byte_perm(v[i].x, v[i].y, 0x7632));
          __syncwarp();
        }
        wait_cnt<true>(&sc->cnt[C_X + 64], 128 * ep);
        if (elect()) mbar_arrive(full0 + 8 * B_X);
        __syncwarp();
      }
      uint32_t lph = 0;
      auto check_tiles = [&](bool second, int n, int st, uint32_t o1, uint32_t d2nd) {
        const uint32_t b1 = pin(sbase + o1), b2 = pin(sbase + o1 + d2nd);
        int i = 0, it = 0;
#pragma unroll 1
        do {
          const uint32_t so = st * (second ? STAGE2 : STAGE);
          mbar_wait(full0 + 8 * (B_LAND + st), (lph >> st) & 1);
          lph ^= 1u << st;
          uint32_t v[20];
#pragma unroll
          for (int k = 0; k < 20; k++) if (!second || k < 10 || k >= 12) v[k] = lds(k < 12 ? b1 + so + k * 1024 : b2 + so + (k - 12) * 1024); else v[k] = tag1;
#pragma unroll
          for (int k = 0; k < 10; k++) v[k] = diff2(v[2 * k], v[2 * k + 1], tag1);
          const uint32_t bad = or3(or3(or3(v[0], v[1], v[2]), or3(v[3], v[4], v[5]), v[6]), v[7], or3(v[8], v[9], 0));
          if (__builtin_expect(any(bad & 1) && ++it < SPIN_MAX, 0)) {
            FAILCNT(2 + second);
            fence_async_smem();
            __syncwarp();
            if (elect()) load_b(second, i, st);
            __syncwarp();
            continue;
          }
          if (elect()) mbar_arrive(full0 + 8 * st);
          if (++st == NST) st = 0;
          i++;
        } while (i < n);
      };
      if (!sw) check_tiles(false, NV1, 0, a1bytes + l * 32 + (l >> 2) * 4, helper ? 4096 : 12288);
      if (sw) {
#pragma unroll 1
        for (int k = 0; k < 2; k++) {
          bar_sync(13 + k, 160);
          if (helper || (first && !k)) continue;
          const uint32_t stg = sbase + (k ? O_U1 : ST0 * STAGE);
          const int kb = (f1 >> 6) + (k ^ flip);
          uint8_t* const ug = sc->u + ((size_t)kb * D_ + d1) * 128;
          if (g2) mbar_wait(full0 + 8 * B_GO, 0);
          if (first) pause(10 * TRK0);
#pragma unroll 1
          for (int i = 0; i < 20480; i += 2048) {
            if (elect()) bulk_st(ug + i, stg + i, 2048);
            pause(k ? TRKC : TRK0);
          }
          if (elect()) red_add(sc->cnt + C_U + kb2_pos(kb), 4);
          bulk_commit_wait();
          if (elect()) { if (!k) mbar_arrive(empty0 + 8 * ST0); TS(k ? 23 : 17); }
          __syncwarp();
        }
        if (elect()) { asm volatile("fence.acq_rel.gpu;" ::: "memory"); red_add(&sc->cnt[C_X], 1); }
        __syncwarp();
      }
      if (g2) {
        if (!sw) check_tiles(true, NV2, 3, 16384 + l * 32 + g * 4, 10240);
        else {
          wait_cnt<true>(&sc->cnt[C_X], NCTA * ep);
          if (elect()) mbar_arrive(full0 + 8 * B_X);
          if (cta == 0) sc->cnt[C_EP + (pin(l) ^ 1)] = ep;
          __syncwarp();
        }
      }
      __syncwarp();
    } else {
      uint32_t ready = 0;
      int st = 0, ph = 1;
#pragma unroll 1
      for (int kb = 0; kb < 32; kb++) {
        const uint8_t* src = upin(sc->h3 + ((size_t)(kb * 18 + (d1 >> 5)) << 12));
        const uint32_t dst = upin(sbase + st * STAGE + a1bytes), lb = full0 + 8 * ((kb < NV1 ? B_LAND : 0) + st);
        if (kb == NV1) { mbar_wait(full0 + 8 * B_X, 0); fence_async_glb(); ready = ~0u; }
        if (rows && (kb >> 1) == 2) mbar_wait(full0 + 8 * (B_S4 - 4 + kb), 0);
        mbar_wait(empty0 + 8 * st, ph);
        if (elect()) mbar_expect(lb, STAGE - a1bytes);
        wait_flags(sc->cnt + C_H3 + l, (kb & 7) + (kb < 8 ? 0 : 8), 64 * ep - 24 * STRESS, ready);
        if (elect()) bulk_ld(dst, src, STAGE - a1bytes, lb);
        ring_next<false>(st, ph);
      }
      if (g2) {
        ready = 0;
        st++;
#pragma unroll 1
        for (int i = 0; i < 36; i++) {
          const int kb = kb2_order(i);
          const uint8_t* src = upin(sc->u + ((size_t)(36 * r + kb) * D_ + d2) * 128);
          const uint32_t dst = upin(sbase + st * STAGE2 + 16384), lb = full0 + 8 * ((i < NV2 ? B_LAND : 0) + st);
          if (i == NV2) { mbar_wait(full0 + 8 * B_X, 1); fence_async_glb(); ready = ~0u; }
          mbar_wait(empty0 + 8 * st, ph);
          if (elect()) mbar_expect(lb, 18432);
          wait_flags(sc->cnt + C_U + 64 * r + l, i & 31, 16 * ep - 8 * STRESS, ready);
          if (elect()) {
            bulk_ld(dst, src, 18432, lb);
            if (i == GOAT) mbar_arrive(full0 + 8 * B_GO);
          }
          ring_next<true>(st, ph);
        }
      }
    }
  } else {
    asm volatile("setmaxnreg.inc.sync.aligned.u32 232;");
    const int wgu = wg;
    constexpr uint32_t sb4 = sbase >> 4;
    const int w = wp & 3;
    Ring rg = {0, 0};
    uint32_t* const x1p = p.out + (size_t)(cta + 128 * ((wp & 3) + 8 * wg)) * 288 + l;
    const int direct = helper || (first && !wg), kbA = (f1 >> 6) + (helper ? 2 : 1) * (wg ^ flip), kbB = (f1 >> 6) + 1;
    const uint32_t uo = (t >> 1) * 2048 + (16 * w + g) * 32 + (((t ^ (g >> 2)) & 1) << 4);
    const uint32_t ad = pin(sbase + (wg ? O_U1 : ST0 * STAGE) + uo);
    uint8_t* const ug0 = pin(sc->u + ((size_t)kbA * D_ + d1) * 128 + uo);
    const int ud1 = upin(helper ? (kbB - kbA) * (D_ * 128) - 3 * 4096 : 0);
    unsigned* const uh = pin(sc->cnt + C_U + kb2_pos(l ? kbB : kbA));
    const int eh = direct && !helper && !l;
    const bool utg = ((t ^ (g >> 2) ^ w) & 1) == 0;
    const uint32_t um0 = pin(utg && g < 4 ? ~1u : ~0u), um1 = pin(utg && g >= 4 ? ~1u : ~0u);
    float acc[96];
    constexpr uint32_t LA = (8192 >> 4) << 16, LB = (4096 >> 4) << 16;
    {
      const float a0 = 0.5f * bf_lo(pin(bia[0])), a1 = 0.5f * bf_lo(pin(bia[1])), b0 = 0.5f * bf_lo(pin(bia[2])), b1 = 0.5f * bf_lo(pin(bia[3]));
#pragma unroll
      for (int i = 0; i < 96; i++) acc[i] = i < 48 ? ((i & 2) ? a1 : a0) : ((i & 2) ? b1 : b0);
      reg_fence(acc);
    }
    if (!helper) gemm_main<0>(acc, sb4 + (wgu ^ flip) * 512 + LA, 0, sb4 + 1024 + LB, wgu, rg, rows, first ? NST : NST - 1, x1p, xr);
    else {
      float ac2[96];
#pragma unroll
      for (int i = 0; i < 96; i++) asm volatile("mov.b32 %0, %1;" : "=f"(ac2[i]) : "f"(acc[i]));
      gemm_main<1>(ac2, sb4 + (wgu ^ flip) * 1024 + LA, sb4 + 512 + LA, sb4 + 1536 + LB, wgu, rg, rows, NST - 1, x1p, xr);
#pragma unroll
      for (int i = 0; i < 96; i++) asm volatile("mov.b32 %0, %1;" : "=f"(acc[i]) : "f"(ac2[i]));
    }
    if (t128 == 0) { TS(wg ? 16 : 6); if (wg) TSC(5); }
    {
      float tp[2] = {0.f, 0.f};
#pragma unroll
      for (int j = 0; j < 12; j++) {
        const float* a = &acc[16 * (j >> 1) + 2 * (j & 1)];
        const float k3 = j < 2 ? (GV ? GK1 : GK3) : fmaf(tp[j & 1], 0.0f, GV ? GK1 : GK3);
        uint32_t o[4];
#pragma unroll
        for (int e = 0; e < 4; e++) {
          const float h0 = a[4 * e], h1 = a[4 * e + 1];
          float z0 = GV ? h0 * fmaf(h0 * h0, GK3, k3) : h0 * fmaf(h0 * k3, h0, GK1), z1 = GV ? h1 * fmaf(h1 * h1, GK3, k3) : h1 * fmaf(h1 * k3, h1, GK1);
          asm("tanh.approx.f32 %0, %0;" : "+f"(z0));
          asm("tanh.approx.f32 %0, %0;" : "+f"(z1));
          if (e == GDEP) tp[j & 1] = z0;
          o[e] = pack_bf16(fmaf(h0, z0, h0), fmaf(h1, z1, h1));
          if ((e >> 1) == (j & 1)) o[e] = bitsel(o[e], (e & 1) ? um1 : um0, tag1);
        }
        if (EH && j == EH) asm volatile("{\n.reg .pred p;\nsetp.ne.u32 p, %1, 0;\n@p red.relaxed.gpu.global.add.u32 [%0], 1;\n}" ::"l"(uh), "r"(eh) : "memory");
        asm volatile("{\n.reg .pred p;\nsetp.ne.u32 p, %6, 0;\n@p st.global.v4.b32 [%0], {%2,%3,%4,%5};\n@!p st.shared.v4.b32 [%1], {%2,%3,%4,%5};\n}"
                     ::"l"(ug0 + (j < 6 ? 0 : ud1) + (j >> 1) * 4096 + (j & 1) * 256), "r"(ad + (j >> 1) * 4096 + (j & 1) * 256),
                       "r"(o[0]), "r"(o[1]), "r"(o[2]), "r"(o[3]), "r"(direct) : "memory");
        if ((j == 5 && helper && !wgu) || (j == 9 && !helper)) break;
      }
      if (!direct) fence_async_smem();
      else if (l <= wgu && (EH == 0 || helper)) red_add(uh, 1);
      __syncwarp();
      bar_arrive(13 + wgu, 160);
      if (t128 == 0) TS(wg ? 29 : 28);
    }
    if (g2) {
      const int mb = wgu ^ r;
      const int odd = z2 & 1;
      uint4 gq[4];
      uint2 gs;
      {
        float a0 = 0.f, a1 = 0.f;
        if (wgu) { a0 = __bfloat162float(p.b2[s2 + 64 * mb + 16 * w + g]); a1 = __bfloat162float(p.b2[s2 + 64 * mb + 16 * w + 8 + g]); }
#pragma unroll
        for (int i = 0; i < 4; i++) gq[i] = lds4(sbase + O_GB + 32 * odd + 64 * i + 16 * t);
        gs = lds2(sbase + O_GB + (odd ? 0 : 256) + 8 * t);
#pragma unroll
        for (int i = 0; i < 72; i++) acc[i] = (i & 2) ? a1 : a0;
      }
      uint32_t* const ob = p.out + (size_t)(s2 + 64 * mb + 16 * w + g) * 288 + (d2 >> 1);
      uint32_t* const oq = pin(ob + 8 * odd + 4 * t);
      uint32_t* const os = pin(ob + (odd ? 0 : 64) + 2 * t);
      rg.st++;
      gemm_main<3>(acc, sb4 + mb * 512 + LA, 0, sb4 + 1024 + ((2048 >> 4) << 16), wgu, rg, rows, NST, x1p, xr);
      if (t128 == 0) { TS(wg ? 20 : 19); if (wg) TSC(22); }
      auto finish = [&](const float* aq, const float* as) {
#pragma unroll
        for (int i = 0; i < 8; i++) {
          const float* a = aq + 16 * (i >> 1) + 2 * (i & 1);
          const uint4 gv = gq[i >> 1];
          red_bf16x8(oq + (i & 1) * 2304 + 16 * (i >> 1), hmul2(gv.x, pack_bf16(a[0], a[1])), hmul2(gv.y, pack_bf16(a[4], a[5])),
                     hmul2(gv.z, pack_bf16(a[8], a[9])), hmul2(gv.w, pack_bf16(a[12], a[13])));
        }
#pragma unroll
        for (int i = 0; i < 2; i++) red_bf16x4(os + i * 2304, hmul2(gs.x, pack_bf16(as[2 * i], as[2 * i + 1])), hmul2(gs.y, pack_bf16(as[2 * i + 4], as[2 * i + 5])));
      };
      if (odd) finish(&acc[8], &acc[0]); else finish(&acc[0], &acc[64]);
      if (t128 == 0) TS(wg ? 7 : 21);
      __syncwarp();
    }
  }
}

typedef CUresult (*EncodeFn)(CUtensorMap*, CUtensorMapDataType, cuuint32_t, void*, const cuuint64_t*, const cuuint64_t*, const cuuint32_t*,
                             const cuuint32_t*, CUtensorMapInterleave, CUtensorMapSwizzle, CUtensorMapL2promotion, CUtensorMapFloatOOBfill);

struct Dim { cuuint64_t n, stride; cuuint32_t box; };
template <int RANK>
void make_map(EncodeFn enc, CUtensorMap* m, bool words, int swz, const void* ptr, const Dim (&d)[RANK]) {
  cuuint64_t gd[RANK], gs[RANK];
  cuuint32_t bx[RANK], es[RANK];
  for (int i = 0; i < RANK; i++) { gd[i] = d[i].n; gs[i] = d[i].stride; bx[i] = d[i].box; es[i] = 1; }
  enc(m, words ? CU_TENSOR_MAP_DATA_TYPE_UINT32 : CU_TENSOR_MAP_DATA_TYPE_BFLOAT16, RANK, const_cast<void*>(ptr), gd, gs + 1, bx, es,
      CU_TENSOR_MAP_INTERLEAVE_NONE, static_cast<CUtensorMapSwizzle>(swz),
      swz == 3 ? CU_TENSOR_MAP_L2_PROMOTION_L2_256B : CU_TENSOR_MAP_L2_PROMOTION_NONE, CU_TENSOR_MAP_FLOAT_OOB_FILL_NONE);
}

}

extern "C" void kernel_launch(void* const* d_in, const int* in_sizes, int n_in, void* d_out, int out_size) {
  (void)in_sizes; (void)n_in; (void)out_size;
  static EncodeFn enc = nullptr;
  static void *sptr = nullptr, *tptr = nullptr;
  if (!enc) {
    void* f = nullptr; cudaDriverEntryPointQueryResult qr;
    cudaGetDriverEntryPoint("cuTensorMapEncodeTiled", &f, cudaEnableDefault, &qr);
    enc = reinterpret_cast<EncodeFn>(f);
    cudaFuncSetAttribute(fused_kernel, cudaFuncAttributeMaxDynamicSharedMemorySize, SMEM_BYTES);
    cudaGetSymbolAddress(&sptr, g_s);
    cudaGetSymbolAddress(&tptr, T_TAB);
  }
  Params p;
  p.x = (const __nv_bfloat16*)d_in[0]; p.wr = (const __nv_bfloat16*)d_in[1]; p.wi = (const __nv_bfloat16*)d_in[2];
  p.b1 = (const __nv_bfloat16*)d_in[5]; p.b2 = (const __nv_bfloat16*)d_in[7];
  p.c = (const __nv_bfloat16*)d_in[8]; p.wmod = (const __nv_bfloat16*)d_in[9];
  p.w1 = (const __nv_bfloat16*)d_in[4]; p.w2 = (const __nv_bfloat16*)d_in[6];
  p.out = static_cast<uint32_t*>(d_out); p.s = static_cast<Scratch*>(sptr); p.tab = static_cast<const uint4*>(tptr);
  Maps maps;
  make_map<4>(enc, &maps.w1a, false, 3, p.w1, {{64, 0, 64}, {16, 128 * 2 * F_, 4}, {128, 2 * F_, 16}, {72, 128, 2}});
  make_map<4>(enc, &maps.w1b, false, 3, p.w1, {{64, 0, 64}, {16, 128 * 2 * F_, 4}, {128, 2 * F_, 16}, {72, 128, 3}});
  make_map<3>(enc, &maps.w2, false, 3, p.w2, {{64, 0, 64}, {F_, 2 * S_, 64}, {32, 128, 2}});
  make_map<2>(enc, &maps.z1, true, 0, p.s->z1, {{5120, 0, 40}, {120, 20480, 60}});
  for (int i = 0; i < 2; i++) make_map<2>(enc, &maps.z2[i], true, 0, p.s->z2, {{4800, 0, i ? 16u : 24u}, {128, 19200, 128}});
  for (int i = 0; i < 4; i++) make_map<2>(enc, &maps.wf[i], false, 2 - (i & 1), (i & 2) ? p.wi : p.wr, {{16 * DF_, 0, (i & 1) ? 16u : 32u}, {128, 32 * DF_, 128}});
  make_map<2>(enc, &maps.wm, false, 1, p.wmod, {{6 * D_, 0, 16}, {D_, 12 * D_, 192}});
  make_map<3>(enc, &maps.h3, true, 0, p.s->h3, {{1024, 0, 64}, {144, 4096, 18}, {4, 144 * 4096, 3}});
  fused_kernel<<<NCTA, NTHR, SMEM_BYTES, cudaStreamPerThread>>>(p, maps);
}
```

```cpp
#include <cuda_runtime.h>
#include <cuda_bf16.h>
#include <cuda.h>
#include <stdint.h>

namespace {

constexpr int S_ = 2048, D_ = 576, DF_ = 289, F_ = 4608;
constexpr int NCTA = 132, NTHR = 384;
constexpr int STAGE = 36864, NST = 6;
constexpr int STAGE2 = 34816, O_U1 = NST * STAGE2, O_GB = O_U1 + 20480, SMEM_BYTES = 232448;
constexpr uint32_t sbase = 1024, red = sbase + NST * STAGE, full0 = sbase + SMEM_BYTES - 256, empty0 = full0 + 8 * NST;
constexpr int O_NRM = 0, O_B1 = 19456, O_Z1 = 38912, O_P2 = 59392, O_ST = 3 * STAGE;
constexpr int O_RAW = 4 * STAGE;
constexpr int O_IN = 4 * STAGE, O_Y = O_IN + 19456, O_B3 = O_IN + 38912, O_MOD = O_IN + 57344;

__device__ __align__(128) const uint32_t T_TAB[5632] = {
0x3f803f80,0xbf803f80,0x3f803f80,0xbf803f80,0x3f803f80,0xbf803f80,0x3f803f80,0xbf803f80,0x3f803f80,0xbf803f80,0x3f803f80,0xbf803f80,
0x3f803f80,0xbf803f80,0x3f803f80,0xbf803f80,0x3f7f3f80,0xbdc90000,0x3f223f35,0xbf46bf35,0x3f753f7b,0xbe95be48,0x3ef13f0e,0xbf62bf55,
0x3f623f6d,0xbef1bec4,0x3e953ec4,0xbf75bf6d,0x3f463f55,0xbf22bf0e,0x3dc93e48,0xbf7fbf7b,0x3f7b3f80,0xbe480000,0xbe480000,0xbf7bbf80,
0x3f553f6d,0xbf0ebec4,0xbf0ebec4,0xbf55bf6d,0x3f0e3f35,0xbf55bf35,0xbf55bf35,0xbf0ebf35,0x3e483ec4,0xbf7bbf6d,0xbf7bbf6d,0xbe48bec4,
0x3f753f80,0xbe950000,0xbf62bf35,0xbef1bf35,0x3f223f55,0xbf46bf0e,0xbf7fbf7b,0x3dc9be48,0x3dc93ec4,0xbf7fbf6d,0xbf46bf6d,0x3f223ec4,
0xbef1be48,0xbf62bf7b,0xbe95bf0e,0x3f753f55,0x3f6d3f80,0xbec40000,0xbf6dbf80,0x3ec40000,0x3ec43f35,0xbf6dbf35,0xbec4bf35,0x3f6d3f35,
0xbec40000,0xbf6dbf80,0x3ec40000,0x3f6d3f80,0xbf6dbf35,0xbec4bf35,0x3f6d3f35,0x3ec43f35,0x3f623f80,0xbef10000,0xbe95bf35,0x3f753f35,
0x3dc93f0e,0xbf7fbf55,0x3f223e48,0x3f463f7b,0xbf46bec4,0xbf22bf6d,0x3f7f3f6d,0xbdc93ec4,0xbf75bf7b,0x3e95be48,0x3ef13f55,0xbf62bf0e,
0x3f553f80,0xbf0e0000,0x3f0e0000,0x3f553f80,0xbe483ec4,0xbf7bbf6d,0x3f7b3f6d,0xbe483ec4,0xbf7bbf35,0xbe48bf35,0x3e483f35,0xbf7bbf35,
0xbf0ebf6d,0x3f553ec4,0xbf55bec4,0xbf0ebf6d,0x3f463f80,0xbf220000,0x3f7f3f35,0x3dc93f35,0xbef13e48,0xbf62bf7b,0x3e953f55,0xbf75bf0e,
0xbf75bf6d,0x3e95bec4,0xbf62bec4,0xbef1bf6d,0x3dc9bf0e,0x3f7f3f55,0xbf22bf7b,0x3f463e48,0x3f353f80,0xbf350000,0x3f353f80,0xbf350000,
0xbf350000,0xbf35bf80,0xbf350000,0xbf35bf80,0xbf35bf80,0x3f350000,0xbf35bf80,0x3f350000,0x3f350000,0x3f353f80,0x3f350000,0x3f353f80,
0x3f223f80,0xbf460000,0xbdc93f35,0xbf7fbf35,0xbf62be48,0xbef1bf7b,0xbf75bf55,0x3e95bf0e,0xbe95bf6d,0x3f753ec4,0x3ef1bec4,0x3f623f6d,
0x3f7f3f0e,0x3dc93f55,0x3f463f7b,0xbf223e48,0x3f0e3f80,0xbf550000,0xbf550000,0xbf0ebf80,0xbf7bbec4,0xbe48bf6d,0xbe48bf6d,0x3f7b3ec4,
0x3e48bf35,0x3f7b3f35,0x3f7b3f35,0xbe483f35,0x3f553f6d,0xbf0e3ec4,0xbf0e3ec4,0xbf55bf6d,0x3ef13f80,0xbf620000,0xbf75bf35,0x3e95bf35,
0xbf7fbf0e,0x3dc9bf55,0x3f46be48,0x3f223f7b,0x3f22bec4,0x3f463f6d,0x3dc93f6d,0xbf7fbec4,0x3e953f7b,0xbf75be48,0xbf62bf55,0x3ef1bf0e,
0x3ec43f80,0xbf6d0000,0xbec4bf80,0x3f6d0000,0xbf6dbf35,0x3ec4bf35,0x3f6d3f35,0xbec43f35,0x3f6d0000,0x3ec43f80,0xbf6d0000,0xbec4bf80,
0xbec43f35,0xbf6dbf35,0x3ec4bf35,0x3f6d3f35,0x3e953f80,0xbf750000,0x3ef1bf35,0x3f623f35,0xbf46bf55,0x3f22bf0e,0x3dc93f7b,0xbf7fbe48,
0x3f7f3ec4,0xbdc93f6d,0xbf22bf6d,0x3f46bec4,0xbf623e48,0xbef1bf7b,0x3f753f0e,0xbe953f55,0x3e483f80,0xbf7b0000,0x3f7b0000,0x3e483f80,
0xbf0ebf6d,0x3f55bec4,0xbf553ec4,0xbf0ebf6d,0x3f553f35,0xbf0e3f35,0x3f0ebf35,0x3f553f35,0xbf7bbec4,0x3e48bf6d,0xbe483f6d,0xbf7bbec4,
0x3dc93f80,0xbf7f0000,0x3f463f35,0xbf223f35,0xbe95bf7b,0x3f75be48,0xbf62bf0e,0x3ef1bf55,0x3ef13f6d,0xbf623ec4,0x3f753ec4,0xbe953f6d,
0xbf22bf55,0x3f46bf0e,0xbf7fbe48,0x3dc9bf7b,0x3f80,0xbf800000,0x3f80,0xbf800000,0xbf80,0x3f800000,0xbf80,0x3f800000,
0x3f80,0xbf800000,0x3f80,0xbf800000,0xbf80,0x3f800000,0xbf80,0x3f800000,0xbdc93f80,0xbf7f0000,0xbf463f35,0xbf22bf35,
0x3e95bf7b,0x3f753e48,0x3f62bf0e,0x3ef13f55,0xbef13f6d,0xbf62bec4,0xbf753ec4,0xbe95bf6d,0x3f22bf55,0x3f463f0e,0x3f7fbe48,0x3dc93f7b,
0xbe483f80,0xbf7b0000,0xbf7b0000,0x3e48bf80,0x3f0ebf6d,0x3f553ec4,0x3f553ec4,0xbf0e3f6d,0xbf553f35,0xbf0ebf35,0xbf0ebf35,0x3f55bf35,
0x3f7bbec4,0x3e483f6d,0x3e483f6d,0xbf7b3ec4,0xbe953f80,0xbf750000,0xbef1bf35,0x3f62bf35,0x3f46bf55,0x3f223f0e,0xbdc93f7b,0xbf7f3e48,
0xbf7f3ec4,0xbdc9bf6d,0x3f22bf6d,0x3f463ec4,0x3f623e48,0xbef13f7b,0xbf753f0e,0xbe95bf55,0xbec43f80,0xbf6d0000,0x3ec4bf80,0x3f6d0000,
0x3f6dbf35,0x3ec43f35,0xbf6d3f35,0xbec4bf35,0xbf6d0000,0x3ec4bf80,0x3f6d0000,0xbec43f80,0x3ec43f35,0xbf6d3f35,0xbec4bf35,0x3f6dbf35,
0xbef13f80,0xbf620000,0x3f75bf35,0x3e953f35,0x3f7fbf0e,0x3dc93f55,0xbf46be48,0x3f22bf7b,0xbf22bec4,0x3f46bf6d,0xbdc93f6d,0xbf7f3ec4,
0xbe953f7b,0xbf753e48,0x3f62bf55,0x3ef13f0e,0xbf0e3f80,0xbf550000,0x3f550000,0xbf0e3f80,0x3f7bbec4,0xbe483f6d,0x3e48bf6d,0x3f7bbec4,
0xbe48bf35,0x3f7bbf35,0xbf7b3f35,0xbe48bf35,0xbf553f6d,0xbf0ebec4,0x3f0e3ec4,0xbf553f6d,0xbf223f80,0xbf460000,0x3dc93f35,0xbf7f3f35,
0x3f62be48,0xbef13f7b,0x3f75bf55,0x3e953f0e,0x3e95bf6d,0x3f75bec4,0xbef1bec4,0x3f62bf6d,0xbf7f3f0e,0x3dc9bf55,0xbf463f7b,0xbf22be48,
0xbf353f80,0xbf350000,0xbf353f80,0xbf350000,0x3f350000,0xbf353f80,0x3f350000,0xbf353f80,0x3f35bf80,0x3f350000,0x3f35bf80,0x3f350000,
0xbf350000,0x3f35bf80,0xbf350000,0x3f35bf80,0xbf463f80,0xbf220000,0xbf7f3f35,0x3dc9bf35,0x3ef13e48,0xbf623f7b,0xbe953f55,0xbf753f0e,
0x3f75bf6d,0x3e953ec4,0x3f62bec4,0xbef13f6d,0xbdc9bf0e,0x3f7fbf55,0x3f22bf7b,0x3f46be48,0xbf553f80,0xbf0e0000,0xbf0e0000,0x3f55bf80,
0x3e483ec4,0xbf7b3f6d,0xbf7b3f6d,0xbe48bec4,0x3f7bbf35,0xbe483f35,0xbe483f35,0xbf7b3f35,0x3f0ebf6d,0x3f55bec4,0x3f55bec4,0xbf0e3f6d,
0xbf623f80,0xbef10000,0x3e95bf35,0x3f75bf35,0xbdc93f0e,0xbf7f3f55,0xbf223e48,0x3f46bf7b,0x3f46bec4,0xbf223f6d,0xbf7f3f6d,0xbdc9bec4,
0x3f75bf7b,0x3e953e48,0xbef13f55,0xbf623f0e,0xbf6d3f80,0xbec40000,0x3f6dbf80,0x3ec40000,0xbec43f35,0xbf6d3f35,0x3ec4bf35,0x3f6dbf35,
0x3ec40000,0xbf6d3f80,0xbec40000,0x3f6dbf80,0x3f6dbf35,0xbec43f35,0xbf6d3f35,0x3ec4bf35,0xbf753f80,0xbe950000,0x3f62bf35,0xbef13f35,
0xbf223f55,0xbf463f0e,0x3f7fbf7b,0x3dc93e48,0xbdc93ec4,0xbf7f3f6d,0x3f46bf6d,0x3f22bec4,0x3ef1be48,0xbf623f7b,0x3e95bf0e,0x3f75bf55,
0xbf7b3f80,0xbe480000,0x3e480000,0xbf7b3f80,0xbf553f6d,0xbf0e3ec4,0x3f0ebec4,0xbf553f6d,0xbf0e3f35,0xbf553f35,0x3f55bf35,0xbf0e3f35,
0xbe483ec4,0xbf7b3f6d,0x3f7bbf6d,0xbe483ec4,0xbf7f3f80,0xbdc90000,0xbf223f35,0xbf463f35,0xbf753f7b,0xbe953e48,0xbef13f0e,0xbf623f55,
0xbf623f6d,0xbef13ec4,0xbe953ec4,0xbf753f6d,0xbf463f55,0xbf223f0e,0xbdc93e48,0xbf7f3f7b,0x3f803f80,0xbf803f80,0x3f803f80,0xbf803f80,
0x3f803f80,0xbf803f80,0x3f803f80,0xbf803f80,0x3f803f80,0xbf803f80,0x3f803f80,0xbf803f80,0x3f803f80,0xbf803f80,0x3f803f80,0xbf803f80,
0xbdc90000,0xbf7fbf80,0xbf46bf35,0xbf22bf35,0xbe95be48,0xbf75bf7b,0xbf62bf55,0xbef1bf0e,0xbef1bec4,0xbf62bf6d,0xbf75bf6d,0xbe95bec4,
0xbf22bf0e,0xbf46bf55,0xbf7fbf7b,0xbdc9be48,0xbf7bbf80,0x3e480000,0x3e480000,0x3f7b3f80,0xbf55bf6d,0x3f0e3ec4,0x3f0e3ec4,0x3f553f6d,
0xbf0ebf35,0x3f553f35,0x3f553f35,0x3f0e3f35,0xbe48bec4,0x3f7b3f6d,0x3f7b3f6d,0x3e483ec4,0x3e950000,0x3f753f80,0x3ef13f35,0xbf62bf35,
0x3f463f0e,0x3f223f55,0xbdc93e48,0xbf7fbf7b,0x3f7f3f6d,0x3dc93ec4,0xbf22bec4,0xbf46bf6d,0x3f623f7b,0xbef1be48,0xbf75bf55,0xbe95bf0e,
0x3f6d3f80,0xbec40000,0xbf6dbf80,0x3ec40000,0x3ec43f35,0xbf6dbf35,0xbec4bf35,0x3f6d3f35,0xbec40000,0xbf6dbf80,0x3ec40000,0x3f6d3f80,
0xbf6dbf35,0xbec4bf35,0x3f6d3f35,0x3ec43f35,0xbef10000,0xbf62bf80,0x3f753f35,0x3e953f35,0xbf7fbf55,0xbdc9bf0e,0x3f463f7b,0xbf22be48,
0xbf22bf6d,0x3f463ec4,0xbdc93ec4,0xbf7fbf6d,0x3e95be48,0x3f753f7b,0xbf62bf0e,0xbef1bf55,0xbf55bf80,0x3f0e0000,0xbf0e0000,0xbf55bf80,
0x3e48bec4,0x3f7b3f6d,0xbf7bbf6d,0x3e48bec4,0x3f7b3f35,0x3e483f35,0xbe48bf35,0x3f7b3f35,0x3f0e3f6d,0xbf55bec4,0x3f553ec4,0x3f0e3f6d,
0x3f220000,0x3f463f80,0xbdc9bf35,0x3f7f3f35,0x3f623f7b,0xbef13e48,0x3f753f0e,0x3e953f55,0xbe953ec4,0xbf75bf6d,0x3ef13f6d,0xbf62bec4,
0xbf7fbf55,0x3dc9bf0e,0xbf46be48,0xbf22bf7b,0x3f353f80,0xbf350000,0x3f353f80,0xbf350000,0xbf350000,0xbf35bf80,0xbf350000,0xbf35bf80,
0xbf35bf80,0x3f350000,0xbf35bf80,0x3f350000,0x3f350000,0x3f353f80,0x3f350000,0x3f353f80,0xbf460000,0xbf22bf80,0xbf7fbf35,0x3dc9bf35,
0xbef1bf7b,0x3f623e48,0x3e95bf0e,0x3f753f55,0x3f753ec4,0x3e953f6d,0x3f623f6d,0xbef13ec4,0x3dc93f55,0xbf7fbf0e,0xbf223e48,0xbf46bf7b,
0xbf0ebf80,0x3f550000,0x3f550000,0x3f0e3f80,0x3f7b3ec4,0x3e483f6d,0x3e483f6d,0xbf7bbec4,0xbe483f35,0xbf7bbf35,0xbf7bbf35,0x3e48bf35,
0xbf55bf6d,0x3f0ebec4,0x3f0ebec4,0x3f553f6d,0x3f620000,0x3ef13f80,0xbe953f35,0xbf75bf35,0xbdc93f55,0xbf7fbf0e,0xbf22bf7b,0x3f46be48,
0xbf46bf6d,0x3f22bec4,0x3f7f3ec4,0x3dc93f6d,0x3f753e48,0x3e953f7b,0xbef13f0e,0xbf62bf55,0x3ec43f80,0xbf6d0000,0xbec4bf80,0x3f6d0000,
0xbf6dbf35,0x3ec4bf35,0x3f6d3f35,0xbec43f35,0x3f6d0000,0x3ec43f80,0xbf6d0000,0xbec4bf80,0xbec43f35,0xbf6dbf35,0x3ec4bf35,0x3f6d3f35,
0xbf750000,0xbe95bf80,0x3f623f35,0xbef13f35,0x3f22bf0e,0x3f463f55,0xbf7fbe48,0xbdc9bf7b,0xbdc93f6d,0xbf7fbec4,0x3f46bec4,0x3f223f6d,
0xbef1bf7b,0x3f62be48,0xbe953f55,0xbf75bf0e,0xbe48bf80,0x3f7b0000,0xbf7b0000,0xbe48bf80,0x3f0e3f6d,0xbf553ec4,0x3f55bec4,0x3f0e3f6d,
0xbf55bf35,0x3f0ebf35,0xbf0e3f35,0xbf55bf35,0x3f7b3ec4,0xbe483f6d,0x3e48bf6d,0x3f7b3ec4,0x3f7f0000,0x3dc93f80,0x3f22bf35,0x3f463f35,
0xbf753e48,0xbe95bf7b,0xbef13f55,0xbf62bf0e,0x3f62bec4,0x3ef13f6d,0x3e95bf6d,0x3f753ec4,0xbf463f0e,0xbf22bf55,0xbdc93f7b,0xbf7fbe48,
0x3f80,0xbf800000,0x3f80,0xbf800000,0xbf80,0x3f800000,0xbf80,0x3f800000,0x3f80,0xbf800000,0x3f80,0xbf800000,
0xbf80,0x3f800000,0xbf80,0x3f800000,0xbf7f0000,0x3dc9bf80,0xbf22bf35,0x3f46bf35,0x3f753e48,0xbe953f7b,0x3ef13f55,0xbf623f0e,
0xbf62bec4,0x3ef1bf6d,0xbe95bf6d,0x3f75bec4,0x3f463f0e,0xbf223f55,0x3dc93f7b,0xbf7f3e48,0x3e48bf80,0x3f7b0000,0x3f7b0000,0xbe483f80,
0xbf0e3f6d,0xbf55bec4,0xbf55bec4,0x3f0ebf6d,0x3f55bf35,0x3f0e3f35,0x3f0e3f35,0xbf553f35,0xbf7b3ec4,0xbe48bf6d,0xbe48bf6d,0x3f7bbec4,
0x3f750000,0xbe953f80,0xbf623f35,0xbef1bf35,0xbf22bf0e,0x3f46bf55,0x3f7fbe48,0xbdc93f7b,0x3dc93f6d,0xbf7f3ec4,0xbf46bec4,0x3f22bf6d,
0x3ef1bf7b,0x3f623e48,0x3e953f55,0xbf753f0e,0xbec43f80,0xbf6d0000,0x3ec4bf80,0x3f6d0000,0x3f6dbf35,0x3ec43f35,0xbf6d3f35,0xbec4bf35,
0xbf6d0000,0x3ec4bf80,0x3f6d0000,0xbec43f80,0x3ec43f35,0xbf6d3f35,0xbec4bf35,0x3f6dbf35,0xbf620000,0x3ef1bf80,0x3e953f35,0xbf753f35,
0x3dc93f55,0xbf7f3f0e,0x3f22bf7b,0x3f463e48,0x3f46bf6d,0x3f223ec4,0xbf7f3ec4,0x3dc9bf6d,0xbf753e48,0x3e95bf7b,0x3ef13f0e,0xbf623f55,
0x3f0ebf80,0x3f550000,0xbf550000,0x3f0ebf80,0xbf7b3ec4,0x3e48bf6d,0xbe483f6d,0xbf7b3ec4,0x3e483f35,0xbf7b3f35,0x3f7bbf35,0x3e483f35,
0x3f55bf6d,0x3f0e3ec4,0xbf0ebec4,0x3f55bf6d,0x3f460000,0xbf223f80,0x3f7fbf35,0x3dc93f35,0x3ef1bf7b,0x3f62be48,0xbe95bf0e,0x3f75bf55,
0xbf753ec4,0x3e95bf6d,0xbf623f6d,0xbef1bec4,0xbdc93f55,0xbf7f3f0e,0x3f223e48,0xbf463f7b,0xbf353f80,0xbf350000,0xbf353f80,0xbf350000,
0x3f350000,0xbf353f80,0x3f350000,0xbf353f80,0x3f35bf80,0x3f350000,0x3f35bf80,0x3f350000,0xbf350000,0x3f35bf80,0xbf350000,0x3f35bf80,
0xbf220000,0x3f46bf80,0x3dc9bf35,0x3f7fbf35,0xbf623f7b,0xbef1be48,0xbf753f0e,0x3e95bf55,0x3e953ec4,0xbf753f6d,0xbef13f6d,0xbf623ec4,
0x3f7fbf55,0x3dc93f0e,0x3f46be48,0xbf223f7b,0x3f55bf80,0x3f0e0000,0x3f0e0000,0xbf553f80,0xbe48bec4,0x3f7bbf6d,0x3f7bbf6d,0x3e483ec4,
0xbf7b3f35,0x3e48bf35,0x3e48bf35,0x3f7bbf35,0xbf0e3f6d,0xbf553ec4,0xbf553ec4,0x3f0ebf6d,0x3ef10000,0xbf623f80,0xbf753f35,0x3e95bf35,
0x3f7fbf55,0xbdc93f0e,0xbf463f7b,0xbf223e48,0x3f22bf6d,0x3f46bec4,0x3dc93ec4,0xbf7f3f6d,0xbe95be48,0x3f75bf7b,0x3f62bf0e,0xbef13f55,
0xbf6d3f80,0xbec40000,0x3f6dbf80,0x3ec40000,0xbec43f35,0xbf6d3f35,0x3ec4bf35,0x3f6dbf35,0x3ec40000,0xbf6d3f80,0xbec40000,0x3f6dbf80,
0x3f6dbf35,0xbec43f35,0xbf6d3f35,0x3ec4bf35,0xbe950000,0x3f75bf80,0xbef13f35,0xbf623f35,0xbf463f0e,0x3f22bf55,0x3dc93e48,0xbf7f3f7b,
0xbf7f3f6d,0x3dc9bec4,0x3f22bec4,0xbf463f6d,0xbf623f7b,0xbef13e48,0x3f75bf55,0xbe953f0e,0x3f7bbf80,0x3e480000,0xbe480000,0x3f7bbf80,
0x3f55bf6d,0x3f0ebec4,0xbf0e3ec4,0x3f55bf6d,0x3f0ebf35,0x3f55bf35,0xbf553f35,0x3f0ebf35,0x3e48bec4,0x3f7bbf6d,0xbf7b3f6d,0x3e48bec4,
0x3dc90000,0xbf7f3f80,0x3f46bf35,0xbf223f35,0x3e95be48,0xbf753f7b,0x3f62bf55,0xbef13f0e,0x3ef1bec4,0xbf623f6d,0x3f75bf6d,0xbe953ec4,
0x3f22bf0e,0xbf463f55,0x3f7fbf7b,0xbdc93e48,0x3f803f80,0xbf803f80,0x3f803f80,0xbf803f80,0x3f803f80,0xbf803f80,0x3f803f80,0xbf803f80,
0x3f803f80,0xbf803f80,0x3f803f80,0xbf803f80,0x3f803f80,0xbf803f80,0x3f803f80,0xbf803f80,0xbf7fbf80,0x3dc90000,0xbf22bf35,0x3f463f35,
0xbf75bf7b,0x3e953e48,0xbef1bf0e,0x3f623f55,0xbf62bf6d,0x3ef13ec4,0xbe95bec4,0x3f753f6d,0xbf46bf55,0x3f223f0e,0xbdc9be48,0x3f7f3f7b,
0x3f7b3f80,0xbe480000,0xbe480000,0xbf7bbf80,0x3f553f6d,0xbf0ebec4,0xbf0ebec4,0xbf55bf6d,0x3f0e3f35,0xbf55bf35,0xbf55bf35,0xbf0ebf35,
0x3e483ec4,0xbf7bbf6d,0xbf7bbf6d,0xbe48bec4,0xbf75bf80,0x3e950000,0x3f623f35,0x3ef13f35,0xbf22bf55,0x3f463f0e,0x3f7f3f7b,0xbdc93e48,
0xbdc9bec4,0x3f7f3f6d,0x3f463f6d,0xbf22bec4,0x3ef13e48,0x3f623f7b,0x3e953f0e,0xbf75bf55,0x3f6d3f80,0xbec40000,0xbf6dbf80,0x3ec40000,
0x3ec43f35,0xbf6dbf35,0xbec4bf35,0x3f6d3f35,0xbec40000,0xbf6dbf80,0x3ec40000,0x3f6d3f80,0xbf6dbf35,0xbec4bf35,0x3f6d3f35,0x3ec43f35,
0xbf62bf80,0x3ef10000,0x3e953f35,0xbf75bf35,0xbdc9bf0e,0x3f7f3f55,0xbf22be48,0xbf46bf7b,0x3f463ec4,0x3f223f6d,0xbf7fbf6d,0x3dc9bec4,
0x3f753f7b,0xbe953e48,0xbef1bf55,0x3f623f0e,0x3f553f80,0xbf0e0000,0x3f0e0000,0x3f553f80,0xbe483ec4,0xbf7bbf6d,0x3f7b3f6d,0xbe483ec4,
0xbf7bbf35,0xbe48bf35,0x3e483f35,0xbf7bbf35,0xbf0ebf6d,0x3f553ec4,0xbf55bec4,0xbf0ebf6d,0xbf46bf80,0x3f220000,0xbf7fbf35,0xbdc9bf35,
0x3ef1be48,0x3f623f7b,0xbe95bf55,0x3f753f0e,0x3f753f6d,0xbe953ec4,0x3f623ec4,0x3ef13f6d,0xbdc93f0e,0xbf7fbf55,0x3f223f7b,0xbf46be48,
0x3f353f80,0xbf350000,0x3f353f80,0xbf350000,0xbf350000,0xbf35bf80,0xbf350000,0xbf35bf80,0xbf35bf80,0x3f350000,0xbf35bf80,0x3f350000,
0x3f350000,0x3f353f80,0x3f350000,0x3f353f80,0xbf22bf80,0x3f460000,0x3dc9bf35,0x3f7f3f35,0x3f623e48,0x3ef13f7b,0x3f753f55,0xbe953f0e,
0x3e953f6d,0xbf75bec4,0xbef13ec4,0xbf62bf6d,0xbf7fbf0e,0xbdc9bf55,0xbf46bf7b,0x3f22be48,0x3f0e3f80,0xbf550000,0xbf550000,0xbf0ebf80,
0xbf7bbec4,0xbe48bf6d,0xbe48bf6d,0x3f7b3ec4,0x3e48bf35,0x3f7b3f35,0x3f7b3f35,0xbe483f35,0x3f553f6d,0xbf0e3ec4,0xbf0e3ec4,0xbf55bf6d,
0xbef1bf80,0x3f620000,0x3f753f35,0xbe953f35,0x3f7f3f0e,0xbdc93f55,0xbf463e48,0xbf22bf7b,0xbf223ec4,0xbf46bf6d,0xbdc9bf6d,0x3f7f3ec4,
0xbe95bf7b,0x3f753e48,0x3f623f55,0xbef13f0e,0x3ec43f80,0xbf6d0000,0xbec4bf80,0x3f6d0000,0xbf6dbf35,0x3ec4bf35,0x3f6d3f35,0xbec43f35,
0x3f6d0000,0x3ec43f80,0xbf6d0000,0xbec4bf80,0xbec43f35,0xbf6dbf35,0x3ec4bf35,0x3f6d3f35,0xbe95bf80,0x3f750000,0xbef13f35,0xbf62bf35,
0x3f463f55,0xbf223f0e,0xbdc9bf7b,0x3f7f3e48,0xbf7fbec4,0x3dc9bf6d,0x3f223f6d,0xbf463ec4,0x3f62be48,0x3ef13f7b,0xbf75bf0e,0x3e95bf55,
0x3e483f80,0xbf7b0000,0x3f7b0000,0x3e483f80,0xbf0ebf6d,0x3f55bec4,0xbf553ec4,0xbf0ebf6d,0x3f553f35,0xbf0e3f35,0x3f0ebf35,0x3f553f35,
0xbf7bbec4,0x3e48bf6d,0xbe483f6d,0xbf7bbec4,0xbdc9bf80,0x3f7f0000,0xbf46bf35,0x3f22bf35,0x3e953f7b,0xbf753e48,0x3f623f0e,0xbef13f55,
0xbef1bf6d,0x3f62bec4,0xbf75bec4,0x3e95bf6d,0x3f223f55,0xbf463f0e,0x3f7f3e48,0xbdc93f7b,0x3f80,0xbf800000,0x3f80,0xbf800000,
0xbf80,0x3f800000,0xbf80,0x3f800000,0x3f80,0xbf800000,0x3f80,0xbf800000,0xbf80,0x3f800000,0xbf80,0x3f800000,
0x3dc9bf80,0x3f7f0000,0x3f46bf35,0x3f223f35,0xbe953f7b,0xbf75be48,0xbf623f0e,0xbef1bf55,0x3ef1bf6d,0x3f623ec4,0x3f75bec4,0x3e953f6d,
0xbf223f55,0xbf46bf0e,0xbf7f3e48,0xbdc9bf7b,0xbe483f80,0xbf7b0000,0xbf7b0000,0x3e48bf80,0x3f0ebf6d,0x3f553ec4,0x3f553ec4,0xbf0e3f6d,
0xbf553f35,0xbf0ebf35,0xbf0ebf35,0x3f55bf35,0x3f7bbec4,0x3e483f6d,0x3e483f6d,0xbf7b3ec4,0x3e95bf80,0x3f750000,0x3ef13f35,0xbf623f35,
0xbf463f55,0xbf22bf0e,0x3dc9bf7b,0x3f7fbe48,0x3f7fbec4,0x3dc93f6d,0xbf223f6d,0xbf46bec4,0xbf62be48,0x3ef1bf7b,0x3f75bf0e,0x3e953f55,
0xbec43f80,0xbf6d0000,0x3ec4bf80,0x3f6d0000,0x3f6dbf35,0x3ec43f35,0xbf6d3f35,0xbec4bf35,0xbf6d0000,0x3ec4bf80,0x3f6d0000,0xbec43f80,
0x3ec43f35,0xbf6d3f35,0xbec4bf35,0x3f6dbf35,0x3ef1bf80,0x3f620000,0xbf753f35,0xbe95bf35,0xbf7f3f0e,0xbdc9bf55,0x3f463e48,0xbf223f7b,
0x3f223ec4,0xbf463f6d,0x3dc9bf6d,0x3f7fbec4,0x3e95bf7b,0x3f75be48,0xbf623f55,0xbef1bf0e,0xbf0e3f80,0xbf550000,0x3f550000,0xbf0e3f80,
0x3f7bbec4,0xbe483f6d,0x3e48bf6d,0x3f7bbec4,0xbe48bf35,0x3f7bbf35,0xbf7b3f35,0xbe48bf35,0xbf553f6d,0xbf0ebec4,0x3f0e3ec4,0xbf553f6d,
0x3f22bf80,0x3f460000,0xbdc9bf35,0x3f7fbf35,0xbf623e48,0x3ef1bf7b,0xbf753f55,0xbe95bf0e,0xbe953f6d,0xbf753ec4,0x3ef13ec4,0xbf623f6d,
0x3f7fbf0e,0xbdc93f55,0x3f46bf7b,0x3f223e48,0xbf353f80,0xbf350000,0xbf353f80,0xbf350000,0x3f350000,0xbf353f80,0x3f350000,0xbf353f80,
0x3f35bf80,0x3f350000,0x3f35bf80,0x3f350000,0xbf350000,0x3f35bf80,0xbf350000,0x3f35bf80,0x3f46bf80,0x3f220000,0x3f7fbf35,0xbdc93f35,
0xbef1be48,0x3f62bf7b,0x3e95bf55,0x3f75bf0e,0xbf753f6d,0xbe95bec4,0xbf623ec4,0x3ef1bf6d,0x3dc93f0e,0xbf7f3f55,0xbf223f7b,0xbf463e48,
0xbf553f80,0xbf0e0000,0xbf0e0000,0x3f55bf80,0x3e483ec4,0xbf7b3f6d,0xbf7b3f6d,0xbe48bec4,0x3f7bbf35,0xbe483f35,0xbe483f35,0xbf7b3f35,
0x3f0ebf6d,0x3f55bec4,0x3f55bec4,0xbf0e3f6d,0x3f62bf80,0x3ef10000,0xbe953f35,0xbf753f35,0x3dc9bf0e,0x3f7fbf55,0x3f22be48,0xbf463f7b,
0xbf463ec4,0x3f22bf6d,0x3f7fbf6d,0x3dc93ec4,0xbf753f7b,0xbe95be48,0x3ef1bf55,0x3f62bf0e,0xbf6d3f80,0xbec40000,0x3f6dbf80,0x3ec40000,
0xbec43f35,0xbf6d3f35,0x3ec4bf35,0x3f6dbf35,0x3ec40000,0xbf6d3f80,0xbec40000,0x3f6dbf80,0x3f6dbf35,0xbec43f35,0xbf6d3f35,0x3ec4bf35,
0x3f75bf80,0x3e950000,0xbf623f35,0x3ef1bf35,0x3f22bf55,0x3f46bf0e,0xbf7f3f7b,0xbdc9be48,0x3dc9bec4,0x3f7fbf6d,0xbf463f6d,0xbf223ec4,
0xbef13e48,0x3f62bf7b,0xbe953f0e,0xbf753f55,0xbf7b3f80,0xbe480000,0x3e480000,0xbf7b3f80,0xbf553f6d,0xbf0e3ec4,0x3f0ebec4,0xbf553f6d,
0xbf0e3f35,0xbf553f35,0x3f55bf35,0xbf0e3f35,0xbe483ec4,0xbf7b3f6d,0x3f7bbf6d,0xbe483ec4,0x3f7fbf80,0x3dc90000,0x3f22bf35,0x3f46bf35,
0x3f75bf7b,0x3e95be48,0x3ef1bf0e,0x3f62bf55,0x3f62bf6d,0x3ef1bec4,0x3e95bec4,0x3f75bf6d,0x3f46bf55,0x3f22bf0e,0x3dc9be48,0x3f7fbf7b,
0x3f803f80,0xbf803f80,0x3f803f80,0xbf803f80,0x3f803f80,0xbf803f80,0x3f803f80,0xbf803f80,0x3f803f80,0xbf803f80,0x3f803f80,0xbf803f80,
0x3f803f80,0xbf803f80,0x3f803f80,0xbf803f80,0x3dc90000,0x3f7f3f80,0x3f463f35,0x3f223f35,0x3e953e48,0x3f753f7b,0x3f623f55,0x3ef13f0e,
0x3ef13ec4,0x3f623f6d,0x3f753f6d,0x3e953ec4,0x3f223f0e,0x3f463f55,0x3f7f3f7b,0x3dc93e48,0xbf7bbf80,0x3e480000,0x3e480000,0x3f7b3f80,
0xbf55bf6d,0x3f0e3ec4,0x3f0e3ec4,0x3f553f6d,0xbf0ebf35,0x3f553f35,0x3f553f35,0x3f0e3f35,0xbe48bec4,0x3f7b3f6d,0x3f7b3f6d,0x3e483ec4,
0xbe950000,0xbf75bf80,0xbef1bf35,0x3f623f35,0xbf46bf0e,0xbf22bf55,0x3dc9be48,0x3f7f3f7b,0xbf7fbf6d,0xbdc9bec4,0x3f223ec4,0x3f463f6d,
0xbf62bf7b,0x3ef13e48,0x3f753f55,0x3e953f0e,0x3f6d3f80,0xbec40000,0xbf6dbf80,0x3ec40000,0x3ec43f35,0xbf6dbf35,0xbec4bf35,0x3f6d3f35,
0xbec40000,0xbf6dbf80,0x3ec40000,0x3f6d3f80,0xbf6dbf35,0xbec4bf35,0x3f6d3f35,0x3ec43f35,0x3ef10000,0x3f623f80,0xbf75bf35,0xbe95bf35,
0x3f7f3f55,0x3dc93f0e,0xbf46bf7b,0x3f223e48,0x3f223f6d,0xbf46bec4,0x3dc9bec4,0x3f7f3f6d,0xbe953e48,0xbf75bf7b,0x3f623f0e,0x3ef13f55,
0xbf55bf80,0x3f0e0000,0xbf0e0000,0xbf55bf80,0x3e48bec4,0x3f7b3f6d,0xbf7bbf6d,0x3e48bec4,0x3f7b3f35,0x3e483f35,0xbe48bf35,0x3f7b3f35,
0x3f0e3f6d,0xbf55bec4,0x3f553ec4,0x3f0e3f6d,0xbf220000,0xbf46bf80,0x3dc93f35,0xbf7fbf35,0xbf62bf7b,0x3ef1be48,0xbf75bf0e,0xbe95bf55,
0x3e95bec4,0x3f753f6d,0xbef1bf6d,0x3f623ec4,0x3f7f3f55,0xbdc93f0e,0x3f463e48,0x3f223f7b,0x3f353f80,0xbf350000,0x3f353f80,0xbf350000,
0xbf350000,0xbf35bf80,0xbf350000,0xbf35bf80,0xbf35bf80,0x3f350000,0xbf35bf80,0x3f350000,0x3f350000,0x3f353f80,0x3f350000,0x3f353f80,
0x3f460000,0x3f223f80,0x3f7f3f35,0xbdc93f35,0x3ef13f7b,0xbf62be48,0xbe953f0e,0xbf75bf55,0xbf75bec4,0xbe95bf6d,0xbf62bf6d,0x3ef1bec4,
0xbdc9bf55,0x3f7f3f0e,0x3f22be48,0x3f463f7b,0xbf0ebf80,0x3f550000,0x3f550000,0x3f0e3f80,0x3f7b3ec4,0x3e483f6d,0x3e483f6d,0xbf7bbec4,
0xbe483f35,0xbf7bbf35,0xbf7bbf35,0x3e48bf35,0xbf55bf6d,0x3f0ebec4,0x3f0ebec4,0x3f553f6d,0xbf620000,0xbef1bf80,0x3e95bf35,0x3f753f35,
0x3dc9bf55,0x3f7f3f0e,0x3f223f7b,0xbf463e48,0x3f463f6d,0xbf223ec4,0xbf7fbec4,0xbdc9bf6d,0xbf75be48,0xbe95bf7b,0x3ef1bf0e,0x3f623f55,
0x3ec43f80,0xbf6d0000,0xbec4bf80,0x3f6d0000,0xbf6dbf35,0x3ec4bf35,0x3f6d3f35,0xbec43f35,0x3f6d0000,0x3ec43f80,0xbf6d0000,0xbec4bf80,
0xbec43f35,0xbf6dbf35,0x3ec4bf35,0x3f6d3f35,0x3f750000,0x3e953f80,0xbf62bf35,0x3ef1bf35,0xbf223f0e,0xbf46bf55,0x3f7f3e48,0x3dc93f7b,
0x3dc9bf6d,0x3f7f3ec4,0xbf463ec4,0xbf22bf6d,0x3ef13f7b,0xbf623e48,0x3e95bf55,0x3f753f0e,0xbe48bf80,0x3f7b0000,0xbf7b0000,0xbe48bf80,
0x3f0e3f6d,0xbf553ec4,0x3f55bec4,0x3f0e3f6d,0xbf55bf35,0x3f0ebf35,0xbf0e3f35,0xbf55bf35,0x3f7b3ec4,0xbe483f6d,0x3e48bf6d,0x3f7b3ec4,
0xbf7f0000,0xbdc9bf80,0xbf223f35,0xbf46bf35,0x3f75be48,0x3e953f7b,0x3ef1bf55,0x3f623f0e,0xbf623ec4,0xbef1bf6d,0xbe953f6d,0xbf75bec4,
0x3f46bf0e,0x3f223f55,0x3dc9bf7b,0x3f7f3e48,0x3f80,0xbf800000,0x3f80,0xbf800000,0xbf80,0x3f800000,0xbf80,0x3f800000,
0x3f80,0xbf800000,0x3f80,0xbf800000,0xbf80,0x3f800000,0xbf80,0x3f800000,0x3f7f0000,0xbdc93f80,0x3f223f35,0xbf463f35,
0xbf75be48,0x3e95bf7b,0xbef1bf55,0x3f62bf0e,0x3f623ec4,0xbef13f6d,0x3e953f6d,0xbf753ec4,0xbf46bf0e,0x3f22bf55,0xbdc9bf7b,0x3f7fbe48,
0x3e48bf80,0x3f7b0000,0x3f7b0000,0xbe483f80,0xbf0e3f6d,0xbf55bec4,0xbf55bec4,0x3f0ebf6d,0x3f55bf35,0x3f0e3f35,0x3f0e3f35,0xbf553f35,
0xbf7b3ec4,0xbe48bf6d,0xbe48bf6d,0x3f7bbec4,0xbf750000,0x3e95bf80,0x3f62bf35,0x3ef13f35,0x3f223f0e,0xbf463f55,0xbf7f3e48,0x3dc9bf7b,
0xbdc9bf6d,0x3f7fbec4,0x3f463ec4,0xbf223f6d,0xbef13f7b,0xbf62be48,0xbe95bf55,0x3f75bf0e,0xbec43f80,0xbf6d0000,0x3ec4bf80,0x3f6d0000,
0x3f6dbf35,0x3ec43f35,0xbf6d3f35,0xbec4bf35,0xbf6d0000,0x3ec4bf80,0x3f6d0000,0xbec43f80,0x3ec43f35,0xbf6d3f35,0xbec4bf35,0x3f6dbf35,
0x3f620000,0xbef13f80,0xbe95bf35,0x3f75bf35,0xbdc9bf55,0x3f7fbf0e,0xbf223f7b,0xbf46be48,0xbf463f6d,0xbf22bec4,0x3f7fbec4,0xbdc93f6d,
0x3f75be48,0xbe953f7b,0xbef1bf0e,0x3f62bf55,0x3f0ebf80,0x3f550000,0xbf550000,0x3f0ebf80,0xbf7b3ec4,0x3e48bf6d,0xbe483f6d,0xbf7b3ec4,
0x3e483f35,0xbf7b3f35,0x3f7bbf35,0x3e483f35,0x3f55bf6d,0x3f0e3ec4,0xbf0ebec4,0x3f55bf6d,0xbf460000,0x3f22bf80,0xbf7f3f35,0xbdc9bf35,
0xbef13f7b,0xbf623e48,0x3e953f0e,0xbf753f55,0x3f75bec4,0xbe953f6d,0x3f62bf6d,0x3ef13ec4,0x3dc9bf55,0x3f7fbf0e,0xbf22be48,0x3f46bf7b,
0xbf353f80,0xbf350000,0xbf353f80,0xbf350000,0x3f350000,0xbf353f80,0x3f350000,0xbf353f80,0x3f35bf80,0x3f350000,0x3f35bf80,0x3f350000,
0xbf350000,0x3f35bf80,0xbf350000,0x3f35bf80,0x3f220000,0xbf463f80,0xbdc93f35,0xbf7f3f35,0x3f62bf7b,0x3ef13e48,0x3f75bf0e,0xbe953f55,
0xbe95bec4,0x3f75bf6d,0x3ef1bf6d,0x3f62bec4,0xbf7f3f55,0xbdc9bf0e,0xbf463e48,0x3f22bf7b,0x3f55bf80,0x3f0e0000,0x3f0e0000,0xbf553f80,
0xbe48bec4,0x3f7bbf6d,0x3f7bbf6d,0x3e483ec4,0xbf7b3f35,0x3e48bf35,0x3e48bf35,0x3f7bbf35,0xbf0e3f6d,0xbf553ec4,0xbf553ec4,0x3f0ebf6d,
0xbef10000,0x3f62bf80,0x3f75bf35,0xbe953f35,0xbf7f3f55,0x3dc9bf0e,0x3f46bf7b,0x3f22be48,0xbf223f6d,0xbf463ec4,0xbdc9bec4,0x3f7fbf6d,
0x3e953e48,0xbf753f7b,0xbf623f0e,0x3ef1bf55,0xbf6d3f80,0xbec40000,0x3f6dbf80,0x3ec40000,0xbec43f35,0xbf6d3f35,0x3ec4bf35,0x3f6dbf35,
0x3ec40000,0xbf6d3f80,0xbec40000,0x3f6dbf80,0x3f6dbf35,0xbec43f35,0xbf6d3f35,0x3ec4bf35,0x3e950000,0xbf753f80,0x3ef1bf35,0x3f62bf35,
0x3f46bf0e,0xbf223f55,0xbdc9be48,0x3f7fbf7b,0x3f7fbf6d,0xbdc93ec4,0xbf223ec4,0x3f46bf6d,0x3f62bf7b,0x3ef1be48,0xbf753f55,0x3e95bf0e,
0x3f7bbf80,0x3e480000,0xbe480000,0x3f7bbf80,0x3f55bf6d,0x3f0ebec4,0xbf0e3ec4,0x3f55bf6d,0x3f0ebf35,0x3f55bf35,0xbf553f35,0x3f0ebf35,
0x3e48bec4,0x3f7bbf6d,0xbf7b3f6d,0x3e48bec4,0xbdc90000,0x3f7fbf80,0xbf463f35,0x3f22bf35,0xbe953e48,0x3f75bf7b,0xbf623f55,0x3ef1bf0e,
0xbef13ec4,0x3f62bf6d,0xbf753f6d,0x3e95bec4,0xbf223f0e,0x3f46bf55,0xbf7f3f7b,0x3dc9be48,0x40003f80,0x3fb53f80,0x3f80,0xbfb53f80,
0x40004000,0xbfb50000,0x0,0xbfb5c000,0x40004000,0xbfb5c000,0x0,0x3fb50000,0x40004000,0x3fb50000,0x0,0x3fb54000,
0x3fff3f80,0x3fa23f80,0xbe49bf80,0xbfc6bf80,0x3ff53ffb,0xbfe2bec8,0xbf15bec8,0xbf71bffb,0x3fe23fed,0xbf15bfed,0xbf71bf44,0x3ff53f44,
0x3fc63fd5,0x3fff3f8e,0xbfa2bf8e,0x3e493fd5,0x3ffb3f80,0x3f8e3f80,0xbec83f80,0xbfd53f80,0x3fd53fed,0xbffbbf44,0xbf8ebf44,0xbec8bfed,
0x3f8e3fb5,0x3ec8bfb5,0xbfd5bfb5,0x3ffb3fb5,0x3ec83f44,0x3fd53fed,0xbffbbfed,0xbf8e3f44,0x3ff53f80,0x3f713f80,0xbf15bf80,0xbfe2bf80,
0x3fa23fd5,0xbfffbf8e,0xbfc6bf8e,0x3e49bfd5,0x3e493f44,0x3fa2bf44,0xbfffbfed,0x3fc63fed,0xbf71bec8,0x3f153ffb,0xbfe2bffb,0xbff5bec8,
0x3fed3f80,0x3f443f80,0xbf443f80,0xbfed3f80,0x3f443fb5,0xbfedbfb5,0xbfedbfb5,0x3f44bfb5,0xbf440000,0x3fed0000,0xbfedc000,0x3f444000,
0xbfedbfb5,0xbf443fb5,0xbf44bfb5,0xbfedbfb5,0x3fe23f80,0x3f153f80,0xbf71bf80,0xbff5bf80,0x3e493f8e,0xbfc6bfd5,0xbfffbfd5,0x3fa2bf8e,
0xbfc6bf44,0x3fff3f44,0xbfa2bfed,0xbe493fed,0xbff5bffb,0xbfe23ec8,0x3f15bec8,0xbf71bffb,0x3fd53f80,0x3ec83f80,0xbf8e3f80,0xbffb3f80,
0xbec83f44,0xbf8ebfed,0xbffbbfed,0x3fd5bf44,0xbffbbfb5,0x3fd53fb5,0xbec8bfb5,0xbf8e3fb5,0xbf8ebfed,0xbffbbf44,0x3fd53f44,0x3ec8bfed,
0x3fc63f80,0x3e493f80,0xbfa2bf80,0xbfffbf80,0xbf713ec8,0xbf15bffb,0xbfe2bffb,0x3ff5bec8,0xbff5bfed,0x3f713fed,0x3f15bf44,0xbfe23f44,
0x3e49bf8e,0xbfa2bfd5,0x3fff3fd5,0x3fc6bf8e,0x3f80,0xbfb53f80,0xc0003f80,0xbfb53f80,0xc000,0x3fb50000,0x40000000,0xbfb54000,
0x4000,0x3fb5c000,0xc0000000,0x3fb50000,0xc000,0xbfb50000,0x40000000,0x3fb5c000,0xbe493f80,0xbfc63f80,0xbfffbf80,0xbfa2bf80,
0x3f15bffb,0x3f713ec8,0x3ff53ec8,0xbfe23ffb,0xbf713fed,0x3ff5bfed,0xbfe2bf44,0x3f153f44,0x3fa2bfd5,0xbe49bf8e,0x3fc63f8e,0x3fffbfd5,
0xbec83f80,0xbfd53f80,0xbffb3f80,0xbf8e3f80,0x3f8ebfed,0x3ec83f44,0x3fd53f44,0xbffb3fed,0xbfd53fb5,0x3ffbbfb5,0xbf8ebfb5,0xbec83fb5,
0x3ffbbf44,0x3f8ebfed,0x3ec83fed,0x3fd5bf44,0xbf153f80,0xbfe23f80,0xbff5bf80,0xbf71bf80,0x3fc6bfd5,0xbe493f8e,0x3fa23f8e,0xbfff3fd5,
0xbfff3f44,0x3fc6bf44,0xbe49bfed,0xbfa23fed,0x3fe23ec8,0x3ff5bffb,0xbf713ffb,0x3f153ec8,0xbf443f80,0xbfed3f80,0xbfed3f80,0xbf443f80,
0x3fedbfb5,0xbf443fb5,0x3f443fb5,0xbfed3fb5,0xbfed0000,0x3f440000,0x3f44c000,0xbfed4000,0x3f443fb5,0x3fedbfb5,0xbfed3fb5,0xbf443fb5,
0xbf713f80,0xbff53f80,0xbfe2bf80,0xbf15bf80,0x3fffbf8e,0xbfa23fd5,0x3e493fd5,0xbfc63f8e,0xbfa2bf44,0xbe493f44,0x3fc6bfed,0xbfff3fed,
0xbf153ffb,0x3f71bec8,0xbff53ec8,0xbfe23ffb,0xbf8e3f80,0xbffb3f80,0xbfd53f80,0xbec83f80,0x3ffbbf44,0xbfd53fed,0xbec83fed,0xbf8e3f44,
0xbec8bfb5,0xbf8e3fb5,0x3ffbbfb5,0xbfd53fb5,0xbfd53fed,0xbec83f44,0xbf8ebf44,0xbffb3fed,0xbfa23f80,0xbfff3f80,0xbfc6bf80,0xbe49bf80,
0x3fe2bec8,0xbff53ffb,0xbf713ffb,0xbf153ec8,0x3f15bfed,0xbfe23fed,0x3ff5bf44,0xbf713f44,0xbfff3f8e,0xbfc63fd5,0x3e49bfd5,0xbfa23f8e,
0xc0003f80,0xbfb53f80,0x3f80,0x3fb53f80,0xc0004000,0x3fb50000,0x0,0x3fb5c000,0xc0004000,0x3fb5c000,0x0,0xbfb50000,
0xc0004000,0xbfb50000,0x0,0xbfb54000,0xbfff3f80,0xbfa23f80,0x3e49bf80,0x3fc6bf80,0xbff53ffb,0x3fe2bec8,0x3f15bec8,0x3f71bffb,
0xbfe23fed,0x3f15bfed,0x3f71bf44,0xbff53f44,0xbfc63fd5,0xbfff3f8e,0x3fa2bf8e,0xbe493fd5,0xbffb3f80,0xbf8e3f80,0x3ec83f80,0x3fd53f80,
0xbfd53fed,0x3ffbbf44,0x3f8ebf44,0x3ec8bfed,0xbf8e3fb5,0xbec8bfb5,0x3fd5bfb5,0xbffb3fb5,0xbec83f44,0xbfd53fed,0x3ffbbfed,0x3f8e3f44,
0xbff53f80,0xbf713f80,0x3f15bf80,0x3fe2bf80,0xbfa23fd5,0x3fffbf8e,0x3fc6bf8e,0xbe49bfd5,0xbe493f44,0xbfa2bf44,0x3fffbfed,0xbfc63fed,
0x3f71bec8,0xbf153ffb,0x3fe2bffb,0x3ff5bec8,0xbfed3f80,0xbf443f80,0x3f443f80,0x3fed3f80,0xbf443fb5,0x3fedbfb5,0x3fedbfb5,0xbf44bfb5,
0x3f440000,0xbfed0000,0x3fedc000,0xbf444000,0x3fedbfb5,0x3f443fb5,0x3f44bfb5,0x3fedbfb5,0xbfe23f80,0xbf153f80,0x3f71bf80,0x3ff5bf80,
0xbe493f8e,0x3fc6bfd5,0x3fffbfd5,0xbfa2bf8e,0x3fc6bf44,0xbfff3f44,0x3fa2bfed,0x3e493fed,0x3ff5bffb,0x3fe23ec8,0xbf15bec8,0x3f71bffb,
0xbfd53f80,0xbec83f80,0x3f8e3f80,0x3ffb3f80,0x3ec83f44,0x3f8ebfed,0x3ffbbfed,0xbfd5bf44,0x3ffbbfb5,0xbfd53fb5,0x3ec8bfb5,0x3f8e3fb5,
0x3f8ebfed,0x3ffbbf44,0xbfd53f44,0xbec8bfed,0xbfc63f80,0xbe493f80,0x3fa2bf80,0x3fffbf80,0x3f713ec8,0x3f15bffb,0x3fe2bffb,0xbff5bec8,
0x3ff5bfed,0xbf713fed,0xbf15bf44,0x3fe23f44,0xbe49bf8e,0x3fa2bfd5,0xbfff3fd5,0xbfc6bf8e,0x3f80,0x3fb53f80,0x40003f80,0x3fb53f80,
0xc000,0xbfb50000,0xc0000000,0x3fb54000,0x4000,0xbfb5c000,0x40000000,0xbfb50000,0xc000,0x3fb50000,0xc0000000,0xbfb5c000,
0x3e493f80,0x3fc63f80,0x3fffbf80,0x3fa2bf80,0xbf15bffb,0xbf713ec8,0xbff53ec8,0x3fe23ffb,0x3f713fed,0xbff5bfed,0x3fe2bf44,0xbf153f44,
0xbfa2bfd5,0x3e49bf8e,0xbfc63f8e,0xbfffbfd5,0x3ec83f80,0x3fd53f80,0x3ffb3f80,0x3f8e3f80,0xbf8ebfed,0xbec83f44,0xbfd53f44,0x3ffb3fed,
0x3fd53fb5,0xbffbbfb5,0x3f8ebfb5,0x3ec83fb5,0xbffbbf44,0xbf8ebfed,0xbec83fed,0xbfd5bf44,0x3f153f80,0x3fe23f80,0x3ff5bf80,0x3f71bf80,
0xbfc6bfd5,0x3e493f8e,0xbfa23f8e,0x3fff3fd5,0x3fff3f44,0xbfc6bf44,0x3e49bfed,0x3fa23fed,0xbfe23ec8,0xbff5bffb,0x3f713ffb,0xbf153ec8,
0x3f443f80,0x3fed3f80,0x3fed3f80,0x3f443f80,0xbfedbfb5,0x3f443fb5,0xbf443fb5,0x3fed3fb5,0x3fed0000,0xbf440000,0xbf44c000,0x3fed4000,
0xbf443fb5,0xbfedbfb5,0x3fed3fb5,0x3f443fb5,0x3f713f80,0x3ff53f80,0x3fe2bf80,0x3f15bf80,0xbfffbf8e,0x3fa23fd5,0xbe493fd5,0x3fc63f8e,
0x3fa2bf44,0x3e493f44,0xbfc6bfed,0x3fff3fed,0x3f153ffb,0xbf71bec8,0x3ff53ec8,0x3fe23ffb,0x3f8e3f80,0x3ffb3f80,0x3fd53f80,0x3ec83f80,
0xbffbbf44,0x3fd53fed,0x3ec83fed,0x3f8e3f44,0x3ec8bfb5,0x3f8e3fb5,0xbffbbfb5,0x3fd53fb5,0x3fd53fed,0x3ec83f44,0x3f8ebf44,0x3ffb3fed,
0x3fa23f80,0x3fff3f80,0x3fc6bf80,0x3e49bf80,0xbfe2bec8,0x3ff53ffb,0x3f713ffb,0x3f153ec8,0xbf15bfed,0x3fe23fed,0xbff5bf44,0x3f713f44,
0x3fff3f8e,0x3fc63fd5,0xbe49bfd5,0x3fa23f8e,0x40004000,0x3fb54000,0x0,0xbfb50000,0x40004000,0xbfb50000,0x0,0xbfb5c000,
0x40004000,0xbfb5c000,0x0,0x3fb50000,0x40004000,0x3fb50000,0x0,0x3fb54000,0x3fa23fb5,0xbe493fb5,0xbfc6bfb5,0xbfffbfb5,
0x3f713f8e,0xbff5bfd5,0xbfe2bfd5,0x3f15bf8e,0x3f153f44,0x3f71bf44,0xbff5bfed,0x3fe23fed,0x3e493ec8,0x3fc63ffb,0xbfffbffb,0xbfa23ec8,
0xbec80000,0xbfd50000,0xbffbc000,0xbf8ec000,0xbf8ebf44,0xbec8bfed,0xbfd5bfed,0x3ffb3f44,0xbfd5bfb5,0x3ffb3fb5,0xbf8ebfb5,0xbec83fb5,
0xbffbbfed,0xbf8e3f44,0xbec8bf44,0xbfd5bfed,0xbfe2bfb5,0xbff5bfb5,0xbf71bfb5,0x3f15bfb5,0xbfffbffb,0x3fc6bec8,0x3e49bec8,0x3fa23ffb,
0xbfc6bfed,0x3e493fed,0x3fa23f44,0xbfffbf44,0xbf15bf8e,0xbfe2bfd5,0x3ff53fd5,0x3f71bf8e,0xbfedc000,0xbf44c000,0x3f440000,0x3fed0000,
0xbf44bfb5,0x3fed3fb5,0x3fed3fb5,0xbf443fb5,0x3f440000,0xbfed0000,0x3fed4000,0xbf44c000,0x3fed3fb5,0x3f44bfb5,0x3f443fb5,0x3fed3fb5,
0xbf15bfb5,0x3f71bfb5,0x3ff53fb5,0x3fe23fb5,0x3fa23ec8,0x3e493ffb,0x3fc63ffb,0xbfffbec8,0x3fff3fed,0xbfa2bfed,0xbe493f44,0x3fc6bf44,
0x3f713fd5,0x3ff53f8e,0xbfe2bf8e,0xbf153fd5,0x3f8e0000,0x3ffb0000,0x3fd54000,0x3ec84000,0x3ffb3fed,0xbfd53f44,0xbec83f44,0xbf8ebfed,
0x3ec83fb5,0x3f8ebfb5,0xbffbbfb5,0x3fd53fb5,0xbfd5bf44,0xbec83fed,0xbf8ebfed,0xbffbbf44,0x3fff3fb5,0x3fc63fb5,0x3e493fb5,0xbfa23fb5,
0x3f153fd5,0xbfe2bf8e,0xbff5bf8e,0x3f71bfd5,0xbfe2bf44,0x3ff53f44,0xbf71bfed,0xbf153fed,0xbfa2bffb,0xbfffbec8,0x3fc63ec8,0x3e49bffb,
0x4000,0xbfb54000,0xc0000000,0xbfb50000,0xc000,0x3fb50000,0x40000000,0xbfb54000,0x4000,0x3fb5c000,0xc0000000,0x3fb50000,
0xc000,0xbfb50000,0x40000000,0x3fb5c000,0xbfc63fb5,0xbfff3fb5,0xbfa2bfb5,0x3e49bfb5,0x3fe2bf8e,0xbf153fd5,0x3f713fd5,0xbff53f8e,
0xbff53f44,0x3fe2bf44,0xbf15bfed,0xbf713fed,0x3fffbec8,0x3fa2bffb,0x3e493ffb,0x3fc6bec8,0xbffb0000,0xbf8e0000,0x3ec8c000,0x3fd5c000,
0x3fd53f44,0xbffb3fed,0xbf8e3fed,0xbec8bf44,0xbf8ebfb5,0xbec83fb5,0x3fd5bfb5,0xbffb3fb5,0x3ec83fed,0x3fd5bf44,0xbffb3f44,0xbf8e3fed,
0xbf71bfb5,0x3f15bfb5,0x3fe2bfb5,0x3ff5bfb5,0xbe493ffb,0xbfa23ec8,0xbfff3ec8,0x3fc6bffb,0x3fa2bfed,0xbfff3fed,0x3fc63f44,0xbe49bf44,
0xbff53f8e,0xbf713fd5,0xbf15bfd5,0xbfe23f8e,0x3f44c000,0x3fedc000,0x3fed0000,0x3f440000,0xbfed3fb5,0x3f44bfb5,0xbf44bfb5,0x3fedbfb5,
0x3fed0000,0xbf440000,0xbf444000,0x3fedc000,0xbf44bfb5,0xbfed3fb5,0x3fedbfb5,0x3f44bfb5,0x3ff5bfb5,0x3fe2bfb5,0x3f153fb5,0xbf713fb5,
0xbfc6bec8,0x3fffbffb,0x3fa2bffb,0x3e493ec8,0xbe493fed,0x3fc6bfed,0xbfff3f44,0x3fa2bf44,0x3fe2bfd5,0x3f15bf8e,0x3f713f8e,0x3ff5bfd5,
0x3fd50000,0x3ec80000,0xbf8e4000,0xbffb4000,0x3ec8bfed,0x3f8ebf44,0x3ffbbf44,0xbfd53fed,0xbffb3fb5,0x3fd5bfb5,0xbec8bfb5,0xbf8e3fb5,
0x3f8e3f44,0x3ffbbfed,0xbfd53fed,0xbec83f44,0x3e493fb5,0xbfa23fb5,0xbfff3fb5,0xbfc63fb5,0x3ff5bfd5,0xbf713f8e,0x3f153f8e,0xbfe23fd5,
0xbf71bf44,0xbf153f44,0x3fe2bfed,0xbff53fed,0xbfc63ffb,0xbe493ec8,0xbfa2bec8,0xbfff3ffb,0xc0004000,0xbfb54000,0x0,0x3fb50000,
0xc0004000,0x3fb50000,0x0,0x3fb5c000,0xc0004000,0x3fb5c000,0x0,0xbfb50000,0xc0004000,0xbfb50000,0x0,0xbfb54000,
0xbfa23fb5,0x3e493fb5,0x3fc6bfb5,0x3fffbfb5,0xbf713f8e,0x3ff5bfd5,0x3fe2bfd5,0xbf15bf8e,0xbf153f44,0xbf71bf44,0x3ff5bfed,0xbfe23fed,
0xbe493ec8,0xbfc63ffb,0x3fffbffb,0x3fa23ec8,0x3ec80000,0x3fd50000,0x3ffbc000,0x3f8ec000,0x3f8ebf44,0x3ec8bfed,0x3fd5bfed,0xbffb3f44,
0x3fd5bfb5,0xbffb3fb5,0x3f8ebfb5,0x3ec83fb5,0x3ffbbfed,0x3f8e3f44,0x3ec8bf44,0x3fd5bfed,0x3fe2bfb5,0x3ff5bfb5,0x3f71bfb5,0xbf15bfb5,
0x3fffbffb,0xbfc6bec8,0xbe49bec8,0xbfa23ffb,0x3fc6bfed,0xbe493fed,0xbfa23f44,0x3fffbf44,0x3f15bf8e,0x3fe2bfd5,0xbff53fd5,0xbf71bf8e,
0x3fedc000,0x3f44c000,0xbf440000,0xbfed0000,0x3f44bfb5,0xbfed3fb5,0xbfed3fb5,0x3f443fb5,0xbf440000,0x3fed0000,0xbfed4000,0x3f44c000,
0xbfed3fb5,0xbf44bfb5,0xbf443fb5,0xbfed3fb5,0x3f15bfb5,0xbf71bfb5,0xbff53fb5,0xbfe23fb5,0xbfa23ec8,0xbe493ffb,0xbfc63ffb,0x3fffbec8,
0xbfff3fed,0x3fa2bfed,0x3e493f44,0xbfc6bf44,0xbf713fd5,0xbff53f8e,0x3fe2bf8e,0x3f153fd5,0xbf8e0000,0xbffb0000,0xbfd54000,0xbec84000,
0xbffb3fed,0x3fd53f44,0x3ec83f44,0x3f8ebfed,0xbec83fb5,0xbf8ebfb5,0x3ffbbfb5,0xbfd53fb5,0x3fd5bf44,0x3ec83fed,0x3f8ebfed,0x3ffbbf44,
0xbfff3fb5,0xbfc63fb5,0xbe493fb5,0x3fa23fb5,0xbf153fd5,0x3fe2bf8e,0x3ff5bf8e,0xbf71bfd5,0x3fe2bf44,0xbff53f44,0x3f71bfed,0x3f153fed,
0x3fa2bffb,0x3fffbec8,0xbfc63ec8,0xbe49bffb,0x4000,0x3fb54000,0x40000000,0x3fb50000,0xc000,0xbfb50000,0xc0000000,0x3fb54000,
0x4000,0xbfb5c000,0x40000000,0xbfb50000,0xc000,0x3fb50000,0xc0000000,0xbfb5c000,0x3fc63fb5,0x3fff3fb5,0x3fa2bfb5,0xbe49bfb5,
0xbfe2bf8e,0x3f153fd5,0xbf713fd5,0x3ff53f8e,0x3ff53f44,0xbfe2bf44,0x3f15bfed,0x3f713fed,0xbfffbec8,0xbfa2bffb,0xbe493ffb,0xbfc6bec8,
0x3ffb0000,0x3f8e0000,0xbec8c000,0xbfd5c000,0xbfd53f44,0x3ffb3fed,0x3f8e3fed,0x3ec8bf44,0x3f8ebfb5,0x3ec83fb5,0xbfd5bfb5,0x3ffb3fb5,
0xbec83fed,0xbfd5bf44,0x3ffb3f44,0x3f8e3fed,0x3f71bfb5,0xbf15bfb5,0xbfe2bfb5,0xbff5bfb5,0x3e493ffb,0x3fa23ec8,0x3fff3ec8,0xbfc6bffb,
0xbfa2bfed,0x3fff3fed,0xbfc63f44,0x3e49bf44,0x3ff53f8e,0x3f713fd5,0x3f15bfd5,0x3fe23f8e,0xbf44c000,0xbfedc000,0xbfed0000,0xbf440000,
0x3fed3fb5,0xbf44bfb5,0x3f44bfb5,0xbfedbfb5,0xbfed0000,0x3f440000,0x3f444000,0xbfedc000,0x3f44bfb5,0x3fed3fb5,0xbfedbfb5,0xbf44bfb5,
0xbff5bfb5,0xbfe2bfb5,0xbf153fb5,0x3f713fb5,0x3fc6bec8,0xbfffbffb,0xbfa2bffb,0xbe493ec8,0x3e493fed,0xbfc6bfed,0x3fff3f44,0xbfa2bf44,
0xbfe2bfd5,0xbf15bf8e,0xbf713f8e,0xbff5bfd5,0xbfd50000,0xbec80000,0x3f8e4000,0x3ffb4000,0xbec8bfed,0xbf8ebf44,0xbffbbf44,0x3fd53fed,
0x3ffb3fb5,0xbfd5bfb5,0x3ec8bfb5,0x3f8e3fb5,0xbf8e3f44,0xbffbbfed,0x3fd53fed,0x3ec83f44,0xbe493fb5,0x3fa23fb5,0x3fff3fb5,0x3fc63fb5,
0xbff5bfd5,0x3f713f8e,0xbf153f8e,0x3fe23fd5,0x3f71bf44,0x3f153f44,0xbfe2bfed,0x3ff53fed,0x3fc63ffb,0x3e493ec8,0x3fa2bec8,0x3fff3ffb,
0x40004000,0x3fb54000,0x0,0xbfb50000,0x40004000,0xbfb50000,0x0,0xbfb5c000,0x40004000,0xbfb5c000,0x0,0x3fb50000,
0x40004000,0x3fb50000,0x0,0x3fb54000,0xbe490000,0xbfc60000,0xbfffc000,0xbfa2c000,0xbf15bec8,0xbf71bffb,0xbff5bffb,0x3fe23ec8,
0xbf71bf44,0x3ff53f44,0xbfe2bfed,0x3f153fed,0xbfa2bf8e,0x3e493fd5,0xbfc6bfd5,0xbfffbf8e,0xbffbc000,0xbf8ec000,0x3ec80000,0x3fd50000,
0xbfd5bfed,0x3ffb3f44,0x3f8e3f44,0x3ec83fed,0xbf8ebfb5,0xbec83fb5,0x3fd53fb5,0xbffbbfb5,0xbec8bf44,0xbfd5bfed,0x3ffb3fed,0x3f8ebf44,
0x3f150000,0x3fe20000,0x3ff54000,0x3f714000,0x3fc63f8e,0xbe493fd5,0x3fa23fd5,0xbfffbf8e,0x3fff3fed,0xbfc6bfed,0x3e493f44,0x3fa2bf44,
0x3fe23ffb,0x3ff53ec8,0xbf71bec8,0x3f153ffb,0x3fed4000,0x3f444000,0xbf440000,0xbfed0000,0x3f443fb5,0xbfedbfb5,0xbfedbfb5,0x3f44bfb5,
0xbf440000,0x3fed0000,0xbfedc000,0x3f444000,0xbfedbfb5,0xbf443fb5,0xbf44bfb5,0xbfedbfb5,0xbf710000,0xbff50000,0xbfe2c000,0xbf15c000,
0xbfffbfd5,0x3fa2bf8e,0xbe49bf8e,0x3fc63fd5,0xbfa2bfed,0xbe493fed,0x3fc63f44,0xbfffbf44,0x3f15bec8,0xbf71bffb,0x3ff53ffb,0x3fe2bec8,
0xbfd5c000,0xbec8c000,0x3f8e0000,0x3ffb0000,0x3ec8bf44,0x3f8e3fed,0x3ffb3fed,0xbfd53f44,0x3ffb3fb5,0xbfd5bfb5,0x3ec83fb5,0x3f8ebfb5,
0x3f8e3fed,0x3ffb3f44,0xbfd5bf44,0xbec83fed,0x3fa20000,0x3fff0000,0x3fc64000,0x3e494000,0x3fe23ffb,0xbff53ec8,0xbf713ec8,0xbf15bffb,
0xbf153f44,0x3fe2bf44,0xbff5bfed,0x3f713fed,0xbfffbfd5,0xbfc63f8e,0x3e49bf8e,0xbfa2bfd5,0x4000,0xbfb54000,0xc0000000,0xbfb50000,
0xc000,0x3fb50000,0x40000000,0xbfb54000,0x4000,0x3fb5c000,0xc0000000,0x3fb50000,0xc000,0xbfb50000,0x40000000,0x3fb5c000,
0xbfff0000,0xbfa20000,0x3e49c000,0x3fc6c000,0x3ff53ec8,0xbfe23ffb,0xbf153ffb,0xbf71bec8,0xbfe2bf44,0x3f153f44,0x3f71bfed,0xbff53fed,
0x3fc63f8e,0x3fffbfd5,0xbfa23fd5,0x3e493f8e,0x3ec8c000,0x3fd5c000,0x3ffb0000,0x3f8e0000,0xbf8e3fed,0xbec8bf44,0xbfd5bf44,0x3ffbbfed,
0x3fd5bfb5,0xbffb3fb5,0x3f8e3fb5,0x3ec8bfb5,0xbffb3f44,0xbf8e3fed,0xbec8bfed,0xbfd53f44,0x3ff50000,0x3f710000,0xbf154000,0xbfe24000,
0xbfa2bf8e,0x3fffbfd5,0x3fc6bfd5,0xbe493f8e,0x3e493fed,0x3fa2bfed,0xbfff3f44,0x3fc6bf44,0x3f71bffb,0xbf15bec8,0x3fe23ec8,0x3ff5bffb,
0xbf444000,0xbfed4000,0xbfed0000,0xbf440000,0x3fedbfb5,0xbf443fb5,0x3f443fb5,0xbfed3fb5,0xbfed0000,0x3f440000,0x3f44c000,0xbfed4000,
0x3f443fb5,0x3fedbfb5,0xbfed3fb5,0xbf443fb5,0xbfe20000,0xbf150000,0x3f71c000,0x3ff5c000,0x3e493fd5,0xbfc63f8e,0xbfff3f8e,0x3fa2bfd5,
0x3fc6bfed,0xbfff3fed,0x3fa23f44,0x3e49bf44,0xbff53ec8,0xbfe23ffb,0x3f15bffb,0xbf713ec8,0x3f8ec000,0x3ffbc000,0x3fd50000,0x3ec80000,
0xbffb3f44,0x3fd5bfed,0x3ec8bfed,0x3f8ebf44,0x3ec83fb5,0x3f8ebfb5,0xbffb3fb5,0x3fd5bfb5,0x3fd5bfed,0x3ec8bf44,0x3f8e3f44,0x3ffbbfed,
0x3fc60000,0x3e490000,0xbfa24000,0xbfff4000,0x3f71bffb,0x3f15bec8,0x3fe2bec8,0xbff53ffb,0xbff53f44,0x3f71bf44,0x3f15bfed,0xbfe23fed,
0xbe493fd5,0x3fa2bf8e,0xbfff3f8e,0xbfc63fd5,0xc0004000,0xbfb54000,0x0,0x3fb50000,0xc0004000,0x3fb50000,0x0,0x3fb5c000,
0xc0004000,0x3fb5c000,0x0,0xbfb50000,0xc0004000,0xbfb50000,0x0,0xbfb54000,0x3e490000,0x3fc60000,0x3fffc000,0x3fa2c000,
0x3f15bec8,0x3f71bffb,0x3ff5bffb,0xbfe23ec8,0x3f71bf44,0xbff53f44,0x3fe2bfed,0xbf153fed,0x3fa2bf8e,0xbe493fd5,0x3fc6bfd5,0x3fffbf8e,
0x3ffbc000,0x3f8ec000,0xbec80000,0xbfd50000,0x3fd5bfed,0xbffb3f44,0xbf8e3f44,0xbec83fed,0x3f8ebfb5,0x3ec83fb5,0xbfd53fb5,0x3ffbbfb5,
0x3ec8bf44,0x3fd5bfed,0xbffb3fed,0xbf8ebf44,0xbf150000,0xbfe20000,0xbff54000,0xbf714000,0xbfc63f8e,0x3e493fd5,0xbfa23fd5,0x3fffbf8e,
0xbfff3fed,0x3fc6bfed,0xbe493f44,0xbfa2bf44,0xbfe23ffb,0xbff53ec8,0x3f71bec8,0xbf153ffb,0xbfed4000,0xbf444000,0x3f440000,0x3fed0000,
0xbf443fb5,0x3fedbfb5,0x3fedbfb5,0xbf44bfb5,0x3f440000,0xbfed0000,0x3fedc000,0xbf444000,0x3fedbfb5,0x3f443fb5,0x3f44bfb5,0x3fedbfb5,
0x3f710000,0x3ff50000,0x3fe2c000,0x3f15c000,0x3fffbfd5,0xbfa2bf8e,0x3e49bf8e,0xbfc63fd5,0x3fa2bfed,0x3e493fed,0xbfc63f44,0x3fffbf44,
0xbf15bec8,0x3f71bffb,0xbff53ffb,0xbfe2bec8,0x3fd5c000,0x3ec8c000,0xbf8e0000,0xbffb0000,0xbec8bf44,0xbf8e3fed,0xbffb3fed,0x3fd53f44,
0xbffb3fb5,0x3fd5bfb5,0xbec83fb5,0xbf8ebfb5,0xbf8e3fed,0xbffb3f44,0x3fd5bf44,0x3ec83fed,0xbfa20000,0xbfff0000,0xbfc64000,0xbe494000,
0xbfe23ffb,0x3ff53ec8,0x3f713ec8,0x3f15bffb,0x3f153f44,0xbfe2bf44,0x3ff5bfed,0xbf713fed,0x3fffbfd5,0x3fc63f8e,0xbe49bf8e,0x3fa2bfd5,
0x4000,0x3fb54000,0x40000000,0x3fb50000,0xc000,0xbfb50000,0xc0000000,0x3fb54000,0x4000,0xbfb5c000,0x40000000,0xbfb50000,
0xc000,0x3fb50000,0xc0000000,0xbfb5c000,0x3fff0000,0x3fa20000,0xbe49c000,0xbfc6c000,0xbff53ec8,0x3fe23ffb,0x3f153ffb,0x3f71bec8,
0x3fe2bf44,0xbf153f44,0xbf71bfed,0x3ff53fed,0xbfc63f8e,0xbfffbfd5,0x3fa23fd5,0xbe493f8e,0xbec8c000,0xbfd5c000,0xbffb0000,0xbf8e0000,
0x3f8e3fed,0x3ec8bf44,0x3fd5bf44,0xbffbbfed,0xbfd5bfb5,0x3ffb3fb5,0xbf8e3fb5,0xbec8bfb5,0x3ffb3f44,0x3f8e3fed,0x3ec8bfed,0x3fd53f44,
0xbff50000,0xbf710000,0x3f154000,0x3fe24000,0x3fa2bf8e,0xbfffbfd5,0xbfc6bfd5,0x3e493f8e,0xbe493fed,0xbfa2bfed,0x3fff3f44,0xbfc6bf44,
0xbf71bffb,0x3f15bec8,0xbfe23ec8,0xbff5bffb,0x3f444000,0x3fed4000,0x3fed0000,0x3f440000,0xbfedbfb5,0x3f443fb5,0xbf443fb5,0x3fed3fb5,
0x3fed0000,0xbf440000,0xbf44c000,0x3fed4000,0xbf443fb5,0xbfedbfb5,0x3fed3fb5,0x3f443fb5,0x3fe20000,0x3f150000,0xbf71c000,0xbff5c000,
0xbe493fd5,0x3fc63f8e,0x3fff3f8e,0xbfa2bfd5,0xbfc6bfed,0x3fff3fed,0xbfa23f44,0xbe49bf44,0x3ff53ec8,0x3fe23ffb,0xbf15bffb,0x3f713ec8,
0xbf8ec000,0xbffbc000,0xbfd50000,0xbec80000,0x3ffb3f44,0xbfd5bfed,0xbec8bfed,0xbf8ebf44,0xbec83fb5,0xbf8ebfb5,0x3ffb3fb5,0xbfd5bfb5,
0xbfd5bfed,0xbec8bf44,0xbf8e3f44,0xbffbbfed,0xbfc60000,0xbe490000,0x3fa24000,0x3fff4000,0xbf71bffb,0xbf15bec8,0xbfe2bec8,0x3ff53ffb,
0x3ff53f44,0xbf71bf44,0xbf15bfed,0x3fe23fed,0x3e493fd5,0xbfa2bf8e,0x3fff3f8e,0x3fc63fd5,0x40004000,0x3fb54000,0x0,0xbfb50000,
0x40004000,0xbfb50000,0x0,0xbfb5c000,0x40004000,0xbfb5c000,0x0,0x3fb50000,0x40004000,0x3fb50000,0x0,0x3fb54000,
0xbfc6bfb5,0xbfffbfb5,0xbfa2bfb5,0x3e49bfb5,0xbfe2bfd5,0x3f15bf8e,0xbf71bf8e,0x3ff53fd5,0xbff5bfed,0x3fe23fed,0xbf15bf44,0xbf713f44,
0xbfffbffb,0xbfa23ec8,0xbe49bec8,0xbfc6bffb,0x3ec80000,0x3fd50000,0x3ffb4000,0x3f8e4000,0x3f8e3f44,0x3ec83fed,0x3fd53fed,0xbffbbf44,
0x3fd53fb5,0xbffbbfb5,0x3f8e3fb5,0x3ec8bfb5,0x3ffb3fed,0x3f8ebf44,0x3ec83f44,0x3fd53fed,0x3f713fb5,0xbf153fb5,0xbfe2bfb5,0xbff5bfb5,
0xbe493ec8,0xbfa2bffb,0xbfffbffb,0x3fc6bec8,0xbfa2bf44,0x3fff3f44,0xbfc6bfed,0x3e493fed,0xbff5bfd5,0xbf713f8e,0xbf15bf8e,0xbfe2bfd5,
0xbfedc000,0xbf44c000,0x3f440000,0x3fed0000,0xbf44bfb5,0x3fed3fb5,0x3fed3fb5,0xbf443fb5,0x3f440000,0xbfed0000,0x3fed4000,0xbf44c000,
0x3fed3fb5,0x3f44bfb5,0x3f443fb5,0x3fed3fb5,0x3ff53fb5,0x3fe23fb5,0x3f153fb5,0xbf713fb5,0x3fc63ffb,0xbfffbec8,0xbfa2bec8,0xbe49bffb,
0xbe493f44,0x3fc6bf44,0xbfffbfed,0x3fa23fed,0xbfe2bf8e,0xbf153fd5,0xbf71bfd5,0xbff5bf8e,0xbf8e0000,0xbffb0000,0xbfd5c000,0xbec8c000,
0xbffbbfed,0x3fd5bf44,0x3ec8bf44,0x3f8e3fed,0xbec8bfb5,0xbf8e3fb5,0x3ffb3fb5,0xbfd5bfb5,0x3fd53f44,0x3ec8bfed,0x3f8e3fed,0x3ffb3f44,
0xbe49bfb5,0x3fa2bfb5,0x3fff3fb5,0x3fc63fb5,0x3ff53f8e,0xbf713fd5,0x3f153fd5,0xbfe2bf8e,0x3f713fed,0x3f15bfed,0xbfe2bf44,0x3ff53f44,
0xbfc6bec8,0xbe493ffb,0xbfa2bffb,0xbfffbec8,0x4000,0xbfb54000,0xc0000000,0xbfb50000,0xc000,0x3fb50000,0x40000000,0xbfb54000,
0x4000,0x3fb5c000,0xc0000000,0x3fb50000,0xc000,0xbfb50000,0x40000000,0x3fb5c000,0xbfa2bfb5,0x3e49bfb5,0x3fc6bfb5,0x3fffbfb5,
0x3f713fd5,0xbff53f8e,0xbfe23f8e,0x3f15bfd5,0xbf15bfed,0xbf713fed,0x3ff5bf44,0xbfe23f44,0x3e493ffb,0x3fc6bec8,0xbfff3ec8,0xbfa23ffb,
0x3ffb0000,0x3f8e0000,0xbec84000,0xbfd54000,0xbfd5bf44,0x3ffbbfed,0x3f8ebfed,0x3ec83f44,0x3f8e3fb5,0x3ec8bfb5,0xbfd53fb5,0x3ffbbfb5,
0xbec8bfed,0xbfd53f44,0x3ffbbf44,0x3f8ebfed,0xbfe23fb5,0xbff53fb5,0xbf71bfb5,0x3f15bfb5,0x3fffbec8,0xbfc63ffb,0xbe493ffb,0xbfa23ec8,
0xbfc6bf44,0x3e493f44,0x3fa2bfed,0xbfff3fed,0x3f153fd5,0x3fe2bf8e,0xbff53f8e,0xbf713fd5,0x3f44c000,0x3fedc000,0x3fed0000,0x3f440000,
0xbfed3fb5,0x3f44bfb5,0xbf44bfb5,0x3fedbfb5,0x3fed0000,0xbf440000,0xbf444000,0x3fedc000,0xbf44bfb5,0xbfed3fb5,0x3fedbfb5,0x3f44bfb5,
0x3f153fb5,0xbf713fb5,0xbff53fb5,0xbfe23fb5,0x3fa2bffb,0x3e493ec8,0x3fc63ec8,0xbfff3ffb,0xbfff3f44,0x3fa2bf44,0x3e49bfed,0xbfc63fed,
0x3f713f8e,0x3ff5bfd5,0xbfe23fd5,0xbf153f8e,0xbfd50000,0xbec80000,0x3f8ec000,0x3ffbc000,0xbec83fed,0xbf8e3f44,0xbffb3f44,0x3fd5bfed,
0x3ffbbfb5,0xbfd53fb5,0x3ec83fb5,0x3f8ebfb5,0xbf8ebf44,0xbffb3fed,0x3fd5bfed,0x3ec8bf44,0x3fffbfb5,0x3fc6bfb5,0x3e493fb5,0xbfa23fb5,
0xbf15bf8e,0x3fe2bfd5,0x3ff5bfd5,0xbf713f8e,0xbfe23fed,0x3ff5bfed,0xbf71bf44,0xbf153f44,0x3fa23ec8,0x3fffbffb,0xbfc63ffb,0xbe493ec8,
0xc0004000,0xbfb54000,0x0,0x3fb50000,0xc0004000,0x3fb50000,0x0,0x3fb5c000,0xc0004000,0x3fb5c000,0x0,0xbfb50000,
0xc0004000,0xbfb50000,0x0,0xbfb54000,0x3fc6bfb5,0x3fffbfb5,0x3fa2bfb5,0xbe49bfb5,0x3fe2bfd5,0xbf15bf8e,0x3f71bf8e,0xbff53fd5,
0x3ff5bfed,0xbfe23fed,0x3f15bf44,0x3f713f44,0x3fffbffb,0x3fa23ec8,0x3e49bec8,0x3fc6bffb,0xbec80000,0xbfd50000,0xbffb4000,0xbf8e4000,
0xbf8e3f44,0xbec83fed,0xbfd53fed,0x3ffbbf44,0xbfd53fb5,0x3ffbbfb5,0xbf8e3fb5,0xbec8bfb5,0xbffb3fed,0xbf8ebf44,0xbec83f44,0xbfd53fed,
0xbf713fb5,0x3f153fb5,0x3fe2bfb5,0x3ff5bfb5,0x3e493ec8,0x3fa2bffb,0x3fffbffb,0xbfc6bec8,0x3fa2bf44,0xbfff3f44,0x3fc6bfed,0xbe493fed,
0x3ff5bfd5,0x3f713f8e,0x3f15bf8e,0x3fe2bfd5,0x3fedc000,0x3f44c000,0xbf440000,0xbfed0000,0x3f44bfb5,0xbfed3fb5,0xbfed3fb5,0x3f443fb5,
0xbf440000,0x3fed0000,0xbfed4000,0x3f44c000,0xbfed3fb5,0xbf44bfb5,0xbf443fb5,0xbfed3fb5,0xbff53fb5,0xbfe23fb5,0xbf153fb5,0x3f713fb5,
0xbfc63ffb,0x3fffbec8,0x3fa2bec8,0x3e49bffb,0x3e493f44,0xbfc6bf44,0x3fffbfed,0xbfa23fed,0x3fe2bf8e,0x3f153fd5,0x3f71bfd5,0x3ff5bf8e,
0x3f8e0000,0x3ffb0000,0x3fd5c000,0x3ec8c000,0x3ffbbfed,0xbfd5bf44,0xbec8bf44,0xbf8e3fed,0x3ec8bfb5,0x3f8e3fb5,0xbffb3fb5,0x3fd5bfb5,
0xbfd53f44,0xbec8bfed,0xbf8e3fed,0xbffb3f44,0x3e49bfb5,0xbfa2bfb5,0xbfff3fb5,0xbfc63fb5,0xbff53f8e,0x3f713fd5,0xbf153fd5,0x3fe2bf8e,
0xbf713fed,0xbf15bfed,0x3fe2bf44,0xbff53f44,0x3fc6bec8,0x3e493ffb,0x3fa2bffb,0x3fffbec8,0x4000,0x3fb54000,0x40000000,0x3fb50000,
0xc000,0xbfb50000,0xc0000000,0x3fb54000,0x4000,0xbfb5c000,0x40000000,0xbfb50000,0xc000,0x3fb50000,0xc0000000,0xbfb5c000,
0x3fa2bfb5,0xbe49bfb5,0xbfc6bfb5,0xbfffbfb5,0xbf713fd5,0x3ff53f8e,0x3fe23f8e,0xbf15bfd5,0x3f15bfed,0x3f713fed,0xbff5bf44,0x3fe23f44,
0xbe493ffb,0xbfc6bec8,0x3fff3ec8,0x3fa23ffb,0xbffb0000,0xbf8e0000,0x3ec84000,0x3fd54000,0x3fd5bf44,0xbffbbfed,0xbf8ebfed,0xbec83f44,
0xbf8e3fb5,0xbec8bfb5,0x3fd53fb5,0xbffbbfb5,0x3ec8bfed,0x3fd53f44,0xbffbbf44,0xbf8ebfed,0x3fe23fb5,0x3ff53fb5,0x3f71bfb5,0xbf15bfb5,
0xbfffbec8,0x3fc63ffb,0x3e493ffb,0x3fa23ec8,0x3fc6bf44,0xbe493f44,0xbfa2bfed,0x3fff3fed,0xbf153fd5,0xbfe2bf8e,0x3ff53f8e,0x3f713fd5,
0xbf44c000,0xbfedc000,0xbfed0000,0xbf440000,0x3fed3fb5,0xbf44bfb5,0x3f44bfb5,0xbfedbfb5,0xbfed0000,0x3f440000,0x3f444000,0xbfedc000,
0x3f44bfb5,0x3fed3fb5,0xbfedbfb5,0xbf44bfb5,0xbf153fb5,0x3f713fb5,0x3ff53fb5,0x3fe23fb5,0xbfa2bffb,0xbe493ec8,0xbfc63ec8,0x3fff3ffb,
0x3fff3f44,0xbfa2bf44,0xbe49bfed,0x3fc63fed,0xbf713f8e,0xbff5bfd5,0x3fe23fd5,0x3f153f8e,0x3fd50000,0x3ec80000,0xbf8ec000,0xbffbc000,
0x3ec83fed,0x3f8e3f44,0x3ffb3f44,0xbfd5bfed,0xbffbbfb5,0x3fd53fb5,0xbec83fb5,0xbf8ebfb5,0x3f8ebf44,0x3ffb3fed,0xbfd5bfed,0xbec8bf44,
0xbfffbfb5,0xbfc6bfb5,0xbe493fb5,0x3fa23fb5,0x3f15bf8e,0xbfe2bfd5,0xbff5bfd5,0x3f713f8e,0x3fe23fed,0xbff5bfed,0x3f71bf44,0x3f153f44,
0xbfa23ec8,0xbfffbffb,0x3fc63ffb,0x3e493ec8,0x80003f80,0x3f800000,0x80003f80,0x3f800000,0x80003f80,0x3f800000,0x80003f80,0x3f800000,
0x80003f80,0x3f800000,0x80003f80,0x3f800000,0x80003f80,0x3f800000,0x80003f80,0x3f800000,0x80003f80,0x3f800000,0x8000bf80,0xbf800000,
0x3f353f35,0x3f35bf35,0xbf35bf35,0xbf353f35,0x3f800000,0xbf80,0xbf800000,0x3f80,0x3f35bf35,0xbf35bf35,0xbf353f35,0x3f353f35,
0x80003f80,0x3f800000,0x80003f80,0x3f800000,0x3f800000,0xbf80,0x3f800000,0xbf80,0x8000bf80,0xbf800000,0x8000bf80,0xbf800000,
0xbf800000,0x3f80,0xbf800000,0x3f80,0x80003f80,0x3f800000,0x8000bf80,0xbf800000,0x3f35bf35,0xbf35bf35,0xbf353f35,0x3f353f35,
0xbf800000,0x3f80,0x3f800000,0xbf80,0x3f353f35,0x3f35bf35,0xbf35bf35,0xbf353f35,0x80003f80,0x3f800000,0x80003f80,0x3f800000,
0x8000bf80,0xbf800000,0x8000bf80,0xbf800000,0x80003f80,0x3f800000,0x80003f80,0x3f800000,0x8000bf80,0xbf800000,0x8000bf80,0xbf800000,
0x80003f80,0x3f800000,0x8000bf80,0xbf800000,0xbf35bf35,0xbf353f35,0x3f353f35,0x3f35bf35,0x3f800000,0xbf80,0xbf800000,0x3f80,
0xbf353f35,0x3f353f35,0x3f35bf35,0xbf35bf35,0x80003f80,0x3f800000,0x80003f80,0x3f800000,0xbf800000,0x3f80,0xbf800000,0x3f80,
0x8000bf80,0xbf800000,0x8000bf80,0xbf800000,0x3f800000,0xbf80,0x3f800000,0xbf80,0x80003f80,0x3f800000,0x8000bf80,0xbf800000,
0xbf353f35,0x3f353f35,0x3f35bf35,0xbf35bf35,0xbf800000,0x3f80,0x3f800000,0xbf80,0xbf35bf35,0xbf353f35,0x3f353f35,0x3f35bf35,
0x3f803f80,0x80008000,0x80008000,0xbf80bf80,0x3f803f80,0x80008000,0x80008000,0xbf80bf80,0x3f803f80,0x80008000,0x80008000,0xbf80bf80,
0x3f803f80,0x80008000,0x80008000,0xbf80bf80,0x3f353f80,0x3f358000,0x3f358000,0xbf35bf80,0xbf350000,0x3f353f80,0x3f353f80,0x3f358000,
0xbf35bf80,0xbf358000,0xbf358000,0x3f353f80,0x3f350000,0xbf35bf80,0xbf35bf80,0xbf358000,0x3f80,0x3f808000,0x3f808000,0x8000bf80,
0xbf80,0xbf808000,0xbf808000,0x80003f80,0x3f80,0x3f808000,0x3f808000,0x8000bf80,0xbf80,0xbf808000,0xbf808000,0x80003f80,
0xbf353f80,0x3f358000,0x3f358000,0x3f35bf80,0x3f350000,0x3f35bf80,0x3f35bf80,0xbf358000,0x3f35bf80,0xbf358000,0xbf358000,0xbf353f80,
0xbf350000,0xbf353f80,0xbf353f80,0x3f358000,0xbf803f80,0x80008000,0x80008000,0x3f80bf80,0xbf803f80,0x80008000,0x80008000,0x3f80bf80,
0xbf803f80,0x80008000,0x80008000,0x3f80bf80,0xbf803f80,0x80008000,0x80008000,0x3f80bf80,0xbf353f80,0xbf358000,0xbf358000,0x3f35bf80,
0x3f350000,0xbf353f80,0xbf353f80,0xbf358000,0x3f35bf80,0x3f358000,0x3f358000,0xbf353f80,0xbf350000,0x3f35bf80,0x3f35bf80,0x3f358000,
0x3f80,0xbf808000,0xbf808000,0x8000bf80,0xbf80,0x3f808000,0x3f808000,0x80003f80,0x3f80,0xbf808000,0xbf808000,0x8000bf80,
0xbf80,0x3f808000,0x3f808000,0x80003f80,0x3f353f80,0xbf358000,0xbf358000,0xbf35bf80,0xbf350000,0xbf35bf80,0xbf35bf80,0x3f358000,
0xbf35bf80,0x3f358000,0x3f358000,0x3f353f80,0x3f350000,0x3f353f80,0x3f353f80,0xbf358000,0x3f800000,0x0,0x3f800000,0x0,
0x3f800000,0x0,0x3f800000,0x0,0x3f800000,0x0,0x3f800000,0x0,0x3f800000,0x0,0x3f800000,0x0,
0x3f800000,0x0,0x3f7fb10f,0xbd48fb30,0x3f7ec46d,0xbdc8bd36,0x3f7d3aac,0xbe164083,0x3f7b14be,0xbe47c5c2,0x3f7853f8,0xbe78cfcc,
0x3f74fa0b,0xbe94a031,0x3f710908,0xbeac7cd4,0x3f800000,0x0,0x3f7ec46d,0xbdc8bd36,0x3f7b14be,0xbe47c5c2,0x3f74fa0b,0xbe94a031,
0x3f6c835e,0xbec3ef15,0x3f61c598,0xbef15aea,0x3f54db31,0xbf0e39da,0x3f45e403,0xbf226799,0x3f800000,0x0,0x3f7d3aac,0xbe164083,
0x3f74fa0b,0xbe94a031,0x3f676bd8,0xbedae880,0x3f54db31,0xbf0e39da,0x3f3daef9,0xbf2beb4a,0x3f226799,0xbf45e403,0x3f039c3d,0xbf5b941a,
0x3f800000,0x0,0x3f7b14be,0xbe47c5c2,0x3f6c835e,0xbec3ef15,0x3f54db31,0xbf0e39da,0x3f3504f3,0xbf3504f3,0x3f0e39da,0xbf54db31,
0x3ec3ef15,0xbf6c835e,0x3e47c5c2,0xbf7b14be,0x3f800000,0x0,0x3f7853f8,0xbe78cfcc,0x3f61c598,0xbef15aea,0x3f3daef9,0xbf2beb4a,
0x3f0e39da,0xbf54db31,0x3eac7cd4,0xbf710908,0x3dc8bd36,0xbf7ec46d,0xbe164083,0xbf7d3aac,0x3f800000,0x0,0x3f74fa0b,0xbe94a031,
0x3f54db31,0xbf0e39da,0x3f226799,0xbf45e403,0x3ec3ef15,0xbf6c835e,0x3dc8bd36,0xbf7ec46d,0xbe47c5c2,0xbf7b14be,0xbef15aea,0xbf61c598,
0x3f800000,0x0,0x3f710908,0xbeac7cd4,0x3f45e403,0xbf226799,0x3f039c3d,0xbf5b941a,0x3e47c5c2,0xbf7b14be,0xbe164083,0xbf7d3aac,
0xbef15aea,0xbf61c598,0xbf3daef9,0xbf2beb4a,0x3f800000,0x0,0x3f800000,0x0,0x3f800000,0x0,0x3f800000,0x0,
0x3f800000,0x0,0x3f800000,0x0,0x3f800000,0x0,0x3f800000,0x0,0x3f6c835e,0xbec3ef15,0x3f676bd8,0xbedae880,
0x3f61c598,0xbef15aea,0x3f5b941a,0xbf039c3d,0x3f54db31,0xbf0e39da,0x3f4d9f02,0xbf187fc0,0x3f45e403,0xbf226799,0x3f3daef9,0xbf2beb4a,
0x3f3504f3,0xbf3504f3,0x3f226799,0xbf45e403,0x3f0e39da,0xbf54db31,0x3ef15aea,0xbf61c598,0x3ec3ef15,0xbf6c835e,0x3e94a031,0xbf74fa0b,
0x3e47c5c2,0xbf7b14be,0x3dc8bd36,0xbf7ec46d,0x3ec3ef15,0xbf6c835e,0x3e78cfcc,0xbf7853f8,0x3dc8bd36,0xbf7ec46d,0xbd48fb30,0xbf7fb10f,
0xbe47c5c2,0xbf7b14be,0xbeac7cd4,0xbf710908,0xbef15aea,0xbf61c598,0xbf187fc0,0xbf4d9f02,0x0,0xbf800000,0xbe47c5c2,0xbf7b14be,
0xbec3ef15,0xbf6c835e,0xbf0e39da,0xbf54db31,0xbf3504f3,0xbf3504f3,0xbf54db31,0xbf0e39da,0xbf6c835e,0xbec3ef15,0xbf7b14be,0xbe47c5c2,
0xbec3ef15,0xbf6c835e,0xbf187fc0,0xbf4d9f02,0xbf45e403,0xbf226799,0xbf676bd8,0xbedae880,0xbf7b14be,0xbe47c5c2,0xbf7fb10f,0x3d48fb30,
0xbf74fa0b,0x3e94a031,0xbf5b941a,0x3f039c3d,0xbf3504f3,0xbf3504f3,0xbf61c598,0xbef15aea,0xbf7b14be,0xbe47c5c2,0xbf7ec46d,0x3dc8bd36,
0xbf6c835e,0x3ec3ef15,0xbf45e403,0x3f226799,0xbf0e39da,0x3f54db31,0xbe94a031,0x3f74fa0b,0xbf6c835e,0xbec3ef15,0xbf7fb10f,0xbd48fb30,
0xbf74fa0b,0x3e94a031,0xbf4d9f02,0x3f187fc0,0xbf0e39da,0x3f54db31,0xbe78cfcc,0x3f7853f8,0x3dc8bd36,0x3f7ec46d,0x3edae880,0x3f676bd8,
0x80003f80,0x3f800000,0x3f800000,0xbf80,0x3ec43f6d,0x3f6dbec4,0x3f6dbec4,0xbec4bf6d,0x3f353f35,0x3f35bf35,0x3f35bf35,0xbf35bf35,
0x3f6d3ec4,0x3ec4bf6d,0x3ec4bf6d,0xbf6dbec4,0x80003f80,0x3f800000,0xbf800000,0x3f80,0x3f6d3ec4,0x3ec4bf6d,0xbec43f6d,0x3f6d3ec4,
0x3f35bf35,0xbf35bf35,0x3f353f35,0x3f35bf35,0xbec4bf6d,0xbf6d3ec4,0x3f6dbec4,0xbec4bf6d,0x80003f80,0x3f800000,0x3f800000,0xbf80,
0x3f6dbec4,0xbec4bf6d,0xbec4bf6d,0xbf6d3ec4,0xbf35bf35,0xbf353f35,0xbf353f35,0x3f353f35,0xbec43f6d,0x3f6d3ec4,0x3f6d3ec4,0x3ec4bf6d,
0x80003f80,0x3f800000,0xbf800000,0x3f80,0x3ec4bf6d,0xbf6dbec4,0x3f6d3ec4,0x3ec4bf6d,0xbf353f35,0x3f353f35,0xbf35bf35,0xbf353f35,
0x3f6dbec4,0xbec4bf6d,0x3ec43f6d,0x3f6dbec4,0x80003f80,0x3f800000,0x3f800000,0xbf80,0xbec4bf6d,0xbf6d3ec4,0xbf6d3ec4,0x3ec43f6d,
0x3f353f35,0x3f35bf35,0x3f35bf35,0xbf35bf35,0xbf6dbec4,0xbec43f6d,0xbec43f6d,0x3f6d3ec4,0x80003f80,0x3f800000,0xbf800000,0x3f80,
0xbf6dbec4,0xbec43f6d,0x3ec4bf6d,0xbf6dbec4,0x3f35bf35,0xbf35bf35,0x3f353f35,0x3f35bf35,0x3ec43f6d,0x3f6dbec4,0xbf6d3ec4,0x3ec43f6d,
0x80003f80,0x3f800000,0x3f800000,0xbf80,0xbf6d3ec4,0x3ec43f6d,0x3ec43f6d,0x3f6dbec4,0xbf35bf35,0xbf353f35,0xbf353f35,0x3f353f35,
0x3ec4bf6d,0xbf6dbec4,0xbf6dbec4,0xbec43f6d,0x80003f80,0x3f800000,0xbf800000,0x3f80,0xbec43f6d,0x3f6d3ec4,0xbf6dbec4,0xbec43f6d,
0xbf353f35,0x3f353f35,0xbf35bf35,0xbf353f35,0xbf6d3ec4,0x3ec43f6d,0xbec4bf6d,0xbf6d3ec4,0x3f803f80,0x80008000,0x80008000,0xbf80bf80,
0x3f803f80,0x80008000,0x80008000,0xbf80bf80,0x3f803f80,0x80008000,0x80008000,0xbf80bf80,0x3f803f80,0x80008000,0x80008000,0xbf80bf80,
0x3ec43f6d,0x3f6d3ec4,0x3f6d3ec4,0xbec4bf6d,0xbf6dbec4,0x3ec43f6d,0x3ec43f6d,0x3f6d3ec4,0xbec4bf6d,0xbf6dbec4,0xbf6dbec4,0x3ec43f6d,
0x3f6d3ec4,0xbec4bf6d,0xbec4bf6d,0xbf6dbec4,0xbf353f35,0x3f353f35,0x3f353f35,0x3f35bf35,0x3f35bf35,0xbf35bf35,0xbf35bf35,0xbf353f35,
0xbf353f35,0x3f353f35,0x3f353f35,0x3f35bf35,0x3f35bf35,0xbf35bf35,0xbf35bf35,0xbf353f35,0xbf6d3ec4,0xbec43f6d,0xbec43f6d,0x3f6dbec4,
0xbec43f6d,0x3f6dbec4,0x3f6dbec4,0x3ec4bf6d,0x3f6dbec4,0x3ec4bf6d,0x3ec4bf6d,0xbf6d3ec4,0x3ec4bf6d,0xbf6d3ec4,0xbf6d3ec4,0xbec43f6d,
0x0,0xbf803f80,0xbf803f80,0x80008000,0x0,0xbf803f80,0xbf803f80,0x80008000,0x0,0xbf803f80,0xbf803f80,0x80008000,
0x0,0xbf803f80,0xbf803f80,0x80008000,0x3f6dbec4,0xbec43f6d,0xbec43f6d,0xbf6d3ec4,0x3ec4bf6d,0x3f6dbec4,0x3f6dbec4,0xbec43f6d,
0xbf6d3ec4,0x3ec4bf6d,0x3ec4bf6d,0x3f6dbec4,0xbec43f6d,0xbf6d3ec4,0xbf6d3ec4,0x3ec4bf6d,0x3f35bf35,0x3f353f35,0x3f353f35,0xbf353f35,
0xbf353f35,0xbf35bf35,0xbf35bf35,0x3f35bf35,0x3f35bf35,0x3f353f35,0x3f353f35,0xbf353f35,0xbf353f35,0xbf35bf35,0xbf35bf35,0x3f35bf35,
0xbec4bf6d,0x3f6d3ec4,0x3f6d3ec4,0x3ec43f6d,0x3f6d3ec4,0x3ec43f6d,0x3ec43f6d,0xbf6dbec4,0x3ec43f6d,0xbf6dbec4,0xbf6dbec4,0xbec4bf6d,
0xbf6dbec4,0xbec4bf6d,0xbec4bf6d,0x3f6d3ec4,0x3f800000,0x0,0x3f7fec43,0xbcc90ab0,0x3f7fb10f,0xbd48fb30,0x3f7f4e6d,0xbd96a905,
0x3f7ec46d,0xbdc8bd36,0x3f7e1324,0xbdfab273,0x3f7d3aac,0xbe164083,0x3f7c3b28,0xbe2f10a2,0x3f800000,0x0,0x3f7f4e6d,0xbd96a905,
0x3f7d3aac,0xbe164083,0x3f79c79d,0xbe605c13,0x3f74fa0b,0xbe94a031,0x3f6ed89e,0xbeb8442a,0x3f676bd8,0xbedae880,0x3f5ebe05,0xbefc5d27,
0x3f800000,0x0,0x3f7e1324,0xbdfab273,0x3f7853f8,0xbe78cfcc,0x3f6ed89e,0xbeb8442a,0x3f61c598,0xbef15aea,0x3f514d3d,0xbf13682a,
0x3f3daef9,0xbf2beb4a,0x3f273656,0xbf41d870,0x3f800000,0x0,0x3f7c3b28,0xbe2f10a2,0x3f710908,0xbeac7cd4,0x3f5ebe05,0xbefc5d27,
0x3f45e403,0xbf226799,0x3f273656,0xbf41d870,0x3f039c3d,0xbf5b941a,0x3eb8442a,0xbf6ed89e,0x3f800000,0x0,0x3f79c79d,0xbe605c13,
0x3f676bd8,0xbedae880,0x3f49d112,0xbf1d7fd1,0x3f226799,0xbf45e403,0x3ee63375,0xbf64aa59,0x3e78cfcc,0xbf7853f8,0x3cc90ab0,0xbf7fec43,
0x3f800000,0x0,0x3f76ba07,0xbe888e93,0x3f5b941a,0xbf039c3d,0x3f3085bb,0xbf396842,0x3ef15aea,0xbf61c598,0x3e605c13,0xbf79c79d,
0xbd48fb30,0xbf7fb10f,0xbea09ae5,0xbf731447,0x3f800000,0x0,0x3f731447,0xbea09ae5,0x3f4d9f02,0xbf187fc0,0x3f13682a,0xbf514d3d,
0x3e94a031,0xbf74fa0b,0xbcc90ab0,0xbf7fec43,0xbeac7cd4,0xbf710908,0xbf1d7fd1,0xbf49d112,0x3f800000,0x0,0x3f6ed89e,0xbeb8442a,
0x3f3daef9,0xbf2beb4a,0x3ee63375,0xbf64aa59,0x3dc8bd36,0xbf7ec46d,0xbe888e93,0xbf76ba07,0xbf187fc0,0xbf4d9f02,0xbf584853,0xbf08f59b,
0x3f7b14be,0xbe47c5c2,0x3f79c79d,0xbe605c13,0x3f7853f8,0xbe78cfcc,0x3f76ba07,0xbe888e93,0x3f74fa0b,0xbe94a031,0x3f731447,0xbea09ae5,
0x3f710908,0xbeac7cd4,0x3f6ed89e,0xbeb8442a,0x3f54db31,0xbf0e39da,0x3f49d112,0xbf1d7fd1,0x3f3daef9,0xbf2beb4a,0x3f3085bb,0xbf396842,
0x3f226799,0xbf45e403,0x3f13682a,0xbf514d3d,0x3f039c3d,0xbf5b941a,0x3ee63375,0xbf64aa59,0x3f0e39da,0xbf54db31,0x3ee63375,0xbf64aa59,
0x3eac7cd4,0xbf710908,0x3e605c13,0xbf79c79d,0x3dc8bd36,0xbf7ec46d,0xbcc90ab0,0xbf7fec43,0xbe164083,0xbf7d3aac,0xbe888e93,0xbf76ba07,
0x3e47c5c2,0xbf7b14be,0x3cc90ab0,0xbf7fec43,0xbe164083,0xbf7d3aac,0xbea09ae5,0xbf731447,0xbef15aea,0xbf61c598,0xbf1d7fd1,0xbf49d112,
0xbf3daef9,0xbf2beb4a,0xbf584853,0xbf08f59b,0xbe47c5c2,0xbf7b14be,0xbecf7bca,0xbf6a09a7,0xbf187fc0,0xbf4d9f02,0xbf41d870,0xbf273656,
0xbf61c598,0xbef15aea,0xbf76ba07,0xbe888e93,0xbf7fb10f,0xbd48fb30,0xbf7c3b28,0x3e2f10a2,0xbf0e39da,0xbf54db31,0xbf41d870,0xbf273656,
0xbf676bd8,0xbedae880,0xbf7c3b28,0xbe2f10a2,0xbf7ec46d,0x3dc8bd36,0xbf6ed89e,0x3eb8442a,0xbf4d9f02,0x3f187fc0,0xbf1d7fd1,0x3f49d112,
0xbf54db31,0xbf0e39da,0xbf76ba07,0xbe888e93,0xbf7fb10f,0x3d48fb30,0xbf6ed89e,0x3eb8442a,0xbf45e403,0x3f226799,0xbf08f59b,0x3f584853,
0xbe78cfcc,0x3f7853f8,0x3d96a905,0x3f7f4e6d,0xbf7b14be,0xbe47c5c2,0xbf7c3b28,0x3e2f10a2,0xbf5b941a,0x3f039c3d,0xbf1d7fd1,0x3f49d112,
0xbe94a031,0x3f74fa0b,0x3d96a905,0x3f7f4e6d,0x3edae880,0x3f676bd8,0x3f396842,0x3f3085bb,0x80003f80,0x80003f80,0x80003f80,0x80003f80,
0x80003f80,0x80003f80,0x80003f80,0x80003f80,0x80003f80,0x80003f80,0x80003f80,0x80003f80,0x80003f80,0x80003f80,0x80003f80,0x80003f80,
0x3f800000,0x3f800000,0x3f800000,0x3f800000,0x3f800000,0x3f800000,0x3f800000,0x3f800000,0x3f800000,0x3f800000,0x3f800000,0x3f800000,
0x3f800000,0x3f800000,0x3f800000,0x3f800000,0x80003f80,0x3f353f35,0x80003f80,0x3f353f35,0x3f800000,0x3f35bf35,0x3f800000,0x3f35bf35,
0x8000bf80,0xbf35bf35,0x8000bf80,0xbf35bf35,0xbf800000,0xbf353f35,0xbf800000,0xbf353f35,0x3f800000,0x3f35bf35,0x3f800000,0x3f35bf35,
0xbf80,0xbf35bf35,0xbf80,0xbf35bf35,0xbf800000,0xbf353f35,0xbf800000,0xbf353f35,0x3f80,0x3f353f35,0x3f80,0x3f353f35,
0x80003f80,0x3f800000,0x80003f80,0x3f800000,0x8000bf80,0xbf800000,0x8000bf80,0xbf800000,0x80003f80,0x3f800000,0x80003f80,0x3f800000,
0x8000bf80,0xbf800000,0x8000bf80,0xbf800000,0x3f800000,0xbf80,0x3f800000,0xbf80,0xbf800000,0x3f80,0xbf800000,0x3f80,
0x3f800000,0xbf80,0x3f800000,0xbf80,0xbf800000,0x3f80,0xbf800000,0x3f80,0x80003f80,0x3f35bf35,0x80003f80,0x3f35bf35,
0xbf800000,0x3f353f35,0xbf800000,0x3f353f35,0x8000bf80,0xbf353f35,0x8000bf80,0xbf353f35,0x3f800000,0xbf35bf35,0x3f800000,0xbf35bf35,
0x3f800000,0xbf35bf35,0x3f800000,0xbf35bf35,0x3f80,0x3f35bf35,0x3f80,0x3f35bf35,0xbf800000,0x3f353f35,0xbf800000,0x3f353f35,
0xbf80,0xbf353f35,0xbf80,0xbf353f35,0x80003f80,0x3ec43f6d,0x8000bf80,0xbec4bf6d,0x3f353f35,0x3f6d3ec4,0xbf35bf35,0xbf6dbec4,
0x3f800000,0x3f6dbec4,0xbf800000,0xbf6d3ec4,0x3f35bf35,0x3ec4bf6d,0xbf353f35,0xbec43f6d,0x3f800000,0x3f6dbec4,0xbf800000,0xbf6d3ec4,
0x3f35bf35,0x3ec4bf6d,0xbf353f35,0xbec43f6d,0xbf80,0xbec4bf6d,0x3f80,0x3ec43f6d,0xbf35bf35,0xbf6dbec4,0x3f353f35,0x3f6d3ec4,
0x80003f80,0x3f6d3ec4,0x8000bf80,0xbf6dbec4,0x3f35bf35,0xbec4bf6d,0xbf353f35,0x3ec43f6d,0xbf800000,0xbec43f6d,0x3f800000,0x3ec4bf6d,
0x3f353f35,0x3f6dbec4,0xbf35bf35,0xbf6d3ec4,0x3f800000,0x3ec4bf6d,0xbf800000,0xbec43f6d,0xbf35bf35,0xbf6d3ec4,0x3f353f35,0x3f6dbec4,
0x3f80,0x3f6d3ec4,0xbf80,0xbf6dbec4,0x3f35bf35,0xbec4bf6d,0xbf353f35,0x3ec43f6d,0x80003f80,0x3f6dbec4,0x8000bf80,0xbf6d3ec4,
0xbf35bf35,0xbec43f6d,0x3f353f35,0x3ec4bf6d,0x3f800000,0xbec4bf6d,0xbf800000,0x3ec43f6d,0xbf353f35,0x3f6d3ec4,0x3f35bf35,0xbf6dbec4,
0x3f800000,0xbec4bf6d,0xbf800000,0x3ec43f6d,0xbf353f35,0x3f6d3ec4,0x3f35bf35,0xbf6dbec4,0xbf80,0xbf6d3ec4,0x3f80,0x3f6dbec4,
0x3f353f35,0x3ec4bf6d,0xbf35bf35,0xbec43f6d,0x80003f80,0x3ec4bf6d,0x8000bf80,0xbec43f6d,0xbf353f35,0x3f6dbec4,0x3f35bf35,0xbf6d3ec4,
0xbf800000,0x3f6d3ec4,0x3f800000,0xbf6dbec4,0xbf35bf35,0x3ec43f6d,0x3f353f35,0xbec4bf6d,0x3f800000,0xbf6dbec4,0xbf800000,0x3f6d3ec4,
0x3f353f35,0xbec4bf6d,0xbf35bf35,0x3ec43f6d,0x3f80,0x3ec4bf6d,0xbf80,0xbec43f6d,0xbf353f35,0x3f6dbec4,0x3f35bf35,0xbf6d3ec4,
0x80003f80,0x8000bf80,0x80003f80,0x8000bf80,0x80003f80,0x8000bf80,0x80003f80,0x8000bf80,0x80003f80,0x8000bf80,0x80003f80,0x8000bf80,
0x80003f80,0x8000bf80,0x80003f80,0x8000bf80,0x3f800000,0xbf800000,0x3f800000,0xbf800000,0x3f800000,0xbf800000,0x3f800000,0xbf800000,
0x3f800000,0xbf800000,0x3f800000,0xbf800000,0x3f800000,0xbf800000,0x3f800000,0xbf800000,0x80003f80,0xbf35bf35,0x80003f80,0xbf35bf35,
0x3f800000,0xbf353f35,0x3f800000,0xbf353f35,0x8000bf80,0x3f353f35,0x8000bf80,0x3f353f35,0xbf800000,0x3f35bf35,0xbf800000,0x3f35bf35,
0x3f800000,0xbf353f35,0x3f800000,0xbf353f35,0xbf80,0x3f353f35,0xbf80,0x3f353f35,0xbf800000,0x3f35bf35,0xbf800000,0x3f35bf35,
0x3f80,0xbf35bf35,0x3f80,0xbf35bf35,0x80003f80,0xbf800000,0x80003f80,0xbf800000,0x8000bf80,0x3f800000,0x8000bf80,0x3f800000,
0x80003f80,0xbf800000,0x80003f80,0xbf800000,0x8000bf80,0x3f800000,0x8000bf80,0x3f800000,0x3f800000,0x3f80,0x3f800000,0x3f80,
0xbf800000,0xbf80,0xbf800000,0xbf80,0x3f800000,0x3f80,0x3f800000,0x3f80,0xbf800000,0xbf80,0xbf800000,0xbf80,
0x80003f80,0xbf353f35,0x80003f80,0xbf353f35,0xbf800000,0xbf35bf35,0xbf800000,0xbf35bf35,0x8000bf80,0x3f35bf35,0x8000bf80,0x3f35bf35,
0x3f800000,0x3f353f35,0x3f800000,0x3f353f35,0x3f800000,0x3f353f35,0x3f800000,0x3f353f35,0x3f80,0xbf353f35,0x3f80,0xbf353f35,
0xbf800000,0xbf35bf35,0xbf800000,0xbf35bf35,0xbf80,0x3f35bf35,0xbf80,0x3f35bf35,0x80003f80,0xbec4bf6d,0x8000bf80,0x3ec43f6d,
0x3f353f35,0xbf6dbec4,0xbf35bf35,0x3f6d3ec4,0x3f800000,0xbf6d3ec4,0xbf800000,0x3f6dbec4,0x3f35bf35,0xbec43f6d,0xbf353f35,0x3ec4bf6d,
0x3f800000,0xbf6d3ec4,0xbf800000,0x3f6dbec4,0x3f35bf35,0xbec43f6d,0xbf353f35,0x3ec4bf6d,0xbf80,0x3ec43f6d,0x3f80,0xbec4bf6d,
0xbf35bf35,0x3f6d3ec4,0x3f353f35,0xbf6dbec4,0x80003f80,0xbf6dbec4,0x8000bf80,0x3f6d3ec4,0x3f35bf35,0x3ec43f6d,0xbf353f35,0xbec4bf6d,
0xbf800000,0x3ec4bf6d,0x3f800000,0xbec43f6d,0x3f353f35,0xbf6d3ec4,0xbf35bf35,0x3f6dbec4,0x3f800000,0xbec43f6d,0xbf800000,0x3ec4bf6d,
0xbf35bf35,0x3f6dbec4,0x3f353f35,0xbf6d3ec4,0x3f80,0xbf6dbec4,0xbf80,0x3f6d3ec4,0x3f35bf35,0x3ec43f6d,0xbf353f35,0xbec4bf6d,
0x80003f80,0xbf6d3ec4,0x8000bf80,0x3f6dbec4,0xbf35bf35,0x3ec4bf6d,0x3f353f35,0xbec43f6d,0x3f800000,0x3ec43f6d,0xbf800000,0xbec4bf6d,
0xbf353f35,0xbf6dbec4,0x3f35bf35,0x3f6d3ec4,0x3f800000,0x3ec43f6d,0xbf800000,0xbec4bf6d,0xbf353f35,0xbf6dbec4,0x3f35bf35,0x3f6d3ec4,
0xbf80,0x3f6dbec4,0x3f80,0xbf6d3ec4,0x3f353f35,0xbec43f6d,0xbf35bf35,0x3ec4bf6d,0x80003f80,0xbec43f6d,0x8000bf80,0x3ec4bf6d,
0xbf353f35,0xbf6d3ec4,0x3f35bf35,0x3f6dbec4,0xbf800000,0xbf6dbec4,0x3f800000,0x3f6d3ec4,0xbf35bf35,0xbec4bf6d,0x3f353f35,0x3ec43f6d,
0x3f800000,0x3f6d3ec4,0xbf800000,0xbf6dbec4,0x3f353f35,0x3ec43f6d,0xbf35bf35,0xbec4bf6d,0x3f80,0xbec43f6d,0xbf80,0x3ec4bf6d,
0xbf353f35,0xbf6d3ec4,0x3f35bf35,0x3f6dbec4,
};
constexpr int TB_F = 0, TB_E = 512, TB_P2 = 1024;

enum { C_EP = 0, C_Z1 = 32, C_Z2 = 96, C_H3 = 128, C_U = 160, C_X = 288, C_TOTAL = 512 };
struct Scratch {
  unsigned cnt[C_TOTAL];
  uint32_t moda[8 * 2 * D_];
  uint32_t mod[4 * D_ + 256];
  uint32_t z1[120 * 5120];
  uint32_t z2[128 * 4800];
  uint8_t h3[32 * 18 * 4096];
  uint8_t u[72 * D_ * 128];
};
__device__ __align__(1024) Scratch g_s;

#define HOLDA 5
#define GOAT 0
#define H3W 0
#define X1K 10
#define PEEK 1
#ifndef NV1
#define NV1 12
#endif
#ifndef NV2
#define NV2 20
#endif
#define GDEP 3
#define TRK0 50
#define W0N 3
#define TRKC 350
#define HD1 150
#define STRESS 0
#define GV 0
#define EH 7
#define KNOB0 0

#define FAILCNT(k) do {} while (0)
#define CK(k) do {} while (0)
#define CKX(k) do {} while (0)
#define TS(k) do {} while (0)
#define TSC(k) do {} while (0)
struct Maps { CUtensorMap z1, z2[2], w1a, w1b, h3, w2, wf[4], wm; };
struct Params {
  const __nv_bfloat16 *x, *c, *wmod;
  Scratch* s;
  const uint4* tab;
  const __nv_bfloat16 *wr, *wi, *w1, *w2, *b1, *b2;
  uint32_t* out;
};

__device__ __forceinline__ uint32_t smem_u32(const void* p) { return (uint32_t)__cvta_generic_to_shared(p); }
__device__ __forceinline__ void mbar_init(uint32_t b, int c) { asm volatile("mbarrier.init.shared::cta.b64 [%0], %1;" ::"r"(b), "r"(c)); }
__device__ __forceinline__ void mbar_expect(uint32_t b, int bytes) { asm volatile("mbarrier.arrive.expect_tx.shared::cta.b64 _, [%0], %1;" ::"r"(b), "r"(bytes) : "memory"); }
__device__ __forceinline__ void mbar_arrive(uint32_t b) { asm volatile("mbarrier.arrive.shared::cta.b64 _, [%0];" ::"r"(b) : "memory"); }
#define MBAR_WAIT(SEM)                                                                                                         \
  asm volatile("{\n.reg .pred p;\n.reg .u32 it;\nmov.u32 it, 0;\nW:\nmbarrier.try_wait.parity" SEM ".shared::cta.b64 p, [%0], %1;\n" \
               "@p bra.uni D;\nadd.u32 it, it, 1;\nsetp.lt.u32 p, it, 0x400000;\n@p bra.uni W;\ntrap;\nD:\n}" ::"r"(b), "r"(ph) : "memory")
__device__ __forceinline__ void mbar_wait(uint32_t b, int ph) { MBAR_WAIT(""); }
__device__ __forceinline__ uint32_t mbar_test(uint32_t b, int ph) {
  uint32_t ok;
  asm volatile("{\n.reg .pred p;\nmbarrier.test_wait.parity.shared::cta.b64 p, [%1], %2;\nselp.u32 %0, 1, 0, p;\n}\n" : "=r"(ok) : "r"(b), "r"(ph) : "memory");
  return ok;
}
__device__ __forceinline__ void tma2d(uint32_t dst, const CUtensorMap* m, int c0, int c1, uint32_t bar) {
  asm volatile("cp.async.bulk.tensor.2d.shared::cluster.global.mbarrier::complete_tx::bytes [%0], [%1, {%3, %4}], [%2];" ::"r"(dst), "l"(m), "r"(bar), "r"(c0), "r"(c1) : "memory");
}
__device__ __forceinline__ uint64_t pol_ef() { uint64_t p; asm("createpolicy.fractional.L2::evict_first.b64 %0, 1.0;" : "=l"(p)); return p; }
__device__ __forceinline__ void tma3d_ef(uint32_t dst, const CUtensorMap* m, int c1, int c2, uint32_t bar) {
  asm volatile("cp.async.bulk.tensor.3d.shared::cluster.global.mbarrier::complete_tx::bytes.L2::cache_hint [%0], [%1, {%3, %4, %5}], [%2], %6;" ::"r"(dst), "l"(m), "r"(bar), "r"(0), "r"(c1), "r"(c2), "l"(pol_ef()) : "memory");
}
__device__ __forceinline__ void tma4d_ef(uint32_t dst, const CUtensorMap* m, int c1, int c2, int c3, uint32_t bar) {
  asm volatile("cp.async.bulk.tensor.4d.shared::cluster.global.mbarrier::complete_tx::bytes.L2::cache_hint [%0], [%1, {%3, %7, %4, %5}], [%2], %6;" ::"r"(dst), "l"(m), "r"(bar), "r"(0), "r"(c2), "r"(c3), "l"(pol_ef()), "r"(c1) : "memory");
}
__device__ __forceinline__ void bulk_ld(uint32_t dst, const void* src, int bytes, uint32_t bar) {
  asm volatile("cp.async.bulk.shared::cluster.global.mbarrier::complete_tx::bytes [%0], [%1], %2, [%3];" ::"r"(dst), "l"(src), "r"(bytes), "r"(bar) : "memory");
}
__device__ __forceinline__ void bulk_st(void* dst, uint32_t src, int bytes) {
  asm volatile("cp.async.bulk.global.shared::cta.bulk_group [%0], [%1], %2;" ::"l"(dst), "r"(src), "r"(bytes) : "memory");
}
__device__ __forceinline__ void tma_st2d(const CUtensorMap* m, uint32_t src, int c0, int c1) {
  asm volatile("cp.async.bulk.tensor.2d.global.shared::cta.bulk_group [%0, {%2, %3}], [%1];" ::"l"(m), "r"(src), "r"(c0), "r"(c1) : "memory");
}
__device__ __forceinline__ void tma_st3d(const CUtensorMap* m, uint32_t src, int c0, int c1, int c2) {
  asm volatile("cp.async.bulk.tensor.3d.global.shared::cta.bulk_group [%0, {%2, %3, %4}], [%1];" ::"l"(m), "r"(src), "r"(c0), "r"(c1), "r"(c2) : "memory");
}
__device__ __forceinline__ void bulk_commit_wait_read() {
  asm volatile("cp.async.bulk.commit_group;" ::: "memory");
  asm volatile("cp.async.bulk.wait_group.read 0;" ::: "memory");
}
__device__ __forceinline__ void bulk_commit_wait() {
  asm volatile("cp.async.bulk.commit_group;" ::: "memory");
  asm volatile("cp.async.bulk.wait_group 0;" ::: "memory");
}
__device__ __forceinline__ void prefetch_l2(const void* p, int bytes) {
  asm volatile("cp.async.bulk.prefetch.L2.global [%0], %1;" ::"l"(p), "r"(bytes) : "memory");
}
__device__ __forceinline__ void wg_fence() { asm volatile("wgmma.fence.sync.aligned;" ::: "memory"); }
__device__ __forceinline__ void wg_commit() { asm volatile("wgmma.commit_group.sync.aligned;" ::: "memory"); }
template <int N> __device__ __forceinline__ void wg_wait() { asm volatile("wgmma.wait_group.sync.aligned %0;" ::"n"(N) : "memory"); }
template <int N> __device__ __forceinline__ void reg_fence(float (&d)[N]) {
#pragma unroll
  for (int i = 0; i < N; i++) asm volatile("" : "+f"(d[i])::"memory");
}
__device__ __forceinline__ void fence_async_smem() { asm volatile("fence.proxy.async.shared::cta;" ::: "memory"); }
__device__ __forceinline__ void fence_async_glb() { asm volatile("fence.proxy.async.global;" ::: "memory"); }
__device__ __forceinline__ uint32_t ld_rlx(const void* p) { uint32_t v; asm volatile("ld.relaxed.gpu.global.b32 %0, [%1];" : "=r"(v) : "l"(p) : "memory"); return v; }
__device__ __forceinline__ uint2 ld_rlx2(const void* p) { uint2 v; asm volatile("ld.relaxed.gpu.global.v2.b32 {%0,%1}, [%2];" : "=r"(v.x), "=r"(v.y) : "l"(p) : "memory"); return v; }
__device__ __forceinline__ uint4 ld_rlx4(const void* p) { uint4 v; asm volatile("ld.relaxed.gpu.global.v4.b32 {%0,%1,%2,%3}, [%4];" : "=r"(v.x), "=r"(v.y), "=r"(v.z), "=r"(v.w) : "l"(p) : "memory"); return v; }
__device__ __forceinline__ uint32_t ld_nc(const void* p) { uint32_t v; asm volatile("ld.global.nc.L1::no_allocate.b32 %0, [%1];" : "=r"(v) : "l"(p) : "memory"); return v; }
__device__ __forceinline__ uint4 ld_nc4(const void* p) { uint4 v; asm volatile("ld.global.nc.v4.b32 {%0,%1,%2,%3}, [%4];" : "=r"(v.x), "=r"(v.y), "=r"(v.z), "=r"(v.w) : "l"(p) : "memory"); return v; }
__device__ __forceinline__ uint32_t lds(uint32_t a) { uint32_t v; asm volatile("ld.shared.b32 %0, [%1];" : "=r"(v) : "r"(a) : "memory"); return v; }
__device__ __forceinline__ uint2 lds2(uint32_t a) { uint2 v; asm volatile("ld.shared.v2.b32 {%0,%1}, [%2];" : "=r"(v.x), "=r"(v.y) : "r"(a) : "memory"); return v; }
__device__ __forceinline__ void lds2_if(int on, uint2& v, uint32_t a) { asm volatile("{\n.reg .pred p;\nsetp.ne.u32 p, %3, 0;\n@p ld.shared.v2.b32 {%0,%1}, [%2];\n}" : "+r"(v.x), "+r"(v.y) : "r"(a), "r"(on) : "memory"); }
__device__ __forceinline__ uint4 lds4(uint32_t a) { uint4 v; asm volatile("ld.shared.v4.b32 {%0,%1,%2,%3}, [%4];" : "=r"(v.x), "=r"(v.y), "=r"(v.z), "=r"(v.w) : "r"(a) : "memory"); return v; }
__device__ __forceinline__ float lds_bf(uint32_t a) { uint32_t v; asm volatile("ld.shared.u16 %0, [%1];" : "=r"(v) : "r"(a) : "memory"); return __uint_as_float(v << 16); }
__device__ __forceinline__ void sts(uint32_t a, uint32_t v) { asm volatile("st.shared.b32 [%0], %1;" ::"r"(a), "r"(v) : "memory"); }
__device__ __forceinline__ void sts2(uint32_t a, uint32_t v0, uint32_t v1) { asm volatile("st.shared.v2.b32 [%0], {%1,%2};" ::"r"(a), "r"(v0), "r"(v1) : "memory"); }
__device__ __forceinline__ void sts4(uint32_t a, uint32_t v0, uint32_t v1, uint32_t v2, uint32_t v3) { asm volatile("st.shared.v4.b32 [%0], {%1,%2,%3,%4};" ::"r"(a), "r"(v0), "r"(v1), "r"(v2), "r"(v3) : "memory"); }
__device__ __forceinline__ void bar_sync(int id, int n) { asm volatile("bar.sync %0, %1;" ::"r"(id), "r"(n) : "memory"); }
__device__ __forceinline__ void bar_arrive(int id, int n) { asm volatile("bar.arrive %0, %1;" ::"r"(id), "r"(n) : "memory"); }
__device__ __forceinline__ void red_add(unsigned* p, unsigned v) { asm volatile("red.relaxed.gpu.global.add.u32 [%0], %1;" ::"l"(p), "r"(v) : "memory"); }
__device__ __forceinline__ bool any(bool p) { return __any_sync(0xffffffffu, p); }
__device__ __forceinline__ void pause(unsigned clks) {
  asm volatile("{\n.reg .pred p;\n.reg .u32 a, b;\nmov.u32 a, %%clock;\nW:\nmov.u32 b, %%clock;\nsub.u32 b, b, a;\nsetp.lt.s32 p, b, %0;\n@p bra.uni W;\n}" ::"r"(clks) : "memory");
}
__device__ __forceinline__ void red_bf16x8(uint32_t* p, uint32_t a, uint32_t b, uint32_t c, uint32_t d) {
  asm volatile("red.relaxed.gpu.global.add.noftz.v4.bf16x2 [%0], {%1,%2,%3,%4};" ::"l"(p), "r"(a), "r"(b), "r"(c), "r"(d) : "memory");
}
__device__ __forceinline__ void red_bf16x4(uint32_t* p, uint32_t a, uint32_t b) {
  asm volatile("red.relaxed.gpu.global.add.noftz.v2.bf16x2 [%0], {%1,%2};" ::"l"(p), "r"(a), "r"(b) : "memory");
}
constexpr int SPIN_MAX = 1 << 20;
__device__ __forceinline__ uint32_t ld_acq(const void* p) { uint32_t v; asm volatile("ld.acquire.gpu.global.b32 %0, [%1];" : "=r"(v) : "l"(p) : "memory"); return v; }
template <bool ACQ = false> __device__ __forceinline__ void wait_cnt(const unsigned* p, unsigned target) {
  int it = 0;
  while (any((int)((ACQ ? ld_acq(p) : ld_rlx(p)) - target) < 0) && ++it < SPIN_MAX) {}
}
__device__ __forceinline__ uint32_t pack_bf16(float lo, float hi) { uint32_t r; asm("cvt.rn.bf16x2.f32 %0, %1, %2;" : "=r"(r) : "f"(hi), "f"(lo)); return r; }
__device__ __forceinline__ float bf_lo(uint32_t v) { return __uint_as_float(v << 16); }
__device__ __forceinline__ float bf_hi(uint32_t v) { return __uint_as_float(v & 0xffff0000u); }
__device__ __forceinline__ uint32_t hadd2(uint32_t a, uint32_t b) { uint32_t r; asm("add.rn.bf16x2 %0, %1, %2;" : "=r"(r) : "r"(a), "r"(b)); return r; }
__device__ __forceinline__ uint32_t hmul2(uint32_t a, uint32_t b) { uint32_t r; asm("mul.rn.bf16x2 %0, %1, %2;" : "=r"(r) : "r"(a), "r"(b)); return r; }
__device__ __forceinline__ uint32_t hfma2(uint32_t a, uint32_t b, uint32_t c) { uint32_t r; asm("fma.rn.bf16x2 %0, %1, %2, %3;" : "=r"(r) : "r"(a), "r"(b), "r"(c)); return r; }
__device__ __forceinline__ float rbf(float x) { uint32_t r; asm("cvt.rn.bf16x2.f32 %0, %1, %2;" : "=r"(r) : "f"(x), "f"(0.0f)); return __uint_as_float(r); }
__device__ __forceinline__ void stmatrix4(uint32_t a, uint32_t r0, uint32_t r1, uint32_t r2, uint32_t r3) {
  asm volatile("stmatrix.sync.aligned.m8n8.x4.shared.b16 [%0], {%1,%2,%3,%4};" ::"r"(a), "r"(r0), "r"(r1), "r"(r2), "r"(r3) : "memory");
}
__device__ __forceinline__ void stmatrix2(uint32_t a, uint32_t r0, uint32_t r1) {
  asm volatile("stmatrix.sync.aligned.m8n8.x2.shared.b16 [%0], {%1,%2};" ::"r"(a), "r"(r0), "r"(r1) : "memory");
}
__device__ __forceinline__ uint32_t movm(uint32_t a) { uint32_t r; asm("movmatrix.sync.aligned.m8n8.trans.b16 %0, %1;" : "=r"(r) : "r"(a)); return r; }
template <bool ACC> __device__ __forceinline__ void mma16(float* d, uint32_t a0, uint32_t a1, uint32_t a2, uint32_t a3, uint32_t b0, uint32_t b1) {
  if (ACC) asm("mma.sync.aligned.m16n8k16.row.col.f32.bf16.bf16.f32 {%0,%1,%2,%3}, {%4,%5,%6,%7}, {%8,%9}, {%0,%1,%2,%3};"
               : "+f"(d[0]), "+f"(d[1]), "+f"(d[2]), "+f"(d[3]) : "r"(a0), "r"(a1), "r"(a2), "r"(a3), "r"(b0), "r"(b1));
  else asm("mma.sync.aligned.m16n8k16.row.col.f32.bf16.bf16.f32 {%0,%1,%2,%3}, {%4,%5,%6,%7}, {%8,%9}, {%10,%10,%10,%10};"
           : "=f"(d[0]), "=f"(d[1]), "=f"(d[2]), "=f"(d[3]) : "r"(a0), "r"(a1), "r"(a2), "r"(a3), "r"(b0), "r"(b1), "f"(0.f));
}
__device__ __forceinline__ uint32_t pin(uint32_t v) { uint32_t r; asm volatile("shfl.sync.bfly.b32 %0, %1, 0, 31, 0xffffffff;" : "=r"(r) : "r"(v)); return r; }
template <class T> __device__ __forceinline__ T* pin(T* p) {
  const uint64_t a = reinterpret_cast<uint64_t>(p);
  return reinterpret_cast<T*>((uint64_t)pin((uint32_t)a) | ((uint64_t)pin((uint32_t)(a >> 32)) << 32));
}
__device__ __forceinline__ uint32_t upin(uint32_t v) { return __shfl_sync(0xffffffffu, v, 0); }
template <class T> __device__ __forceinline__ T* upin(T* p) {
  const uint64_t a = reinterpret_cast<uint64_t>(p);
  return reinterpret_cast<T*>((uint64_t)upin((uint32_t)a) | ((uint64_t)upin((uint32_t)(a >> 32)) << 32));
}
__device__ __forceinline__ bool elect() {
  uint32_t p;
  asm volatile("{\n.reg .pred P;\nelect.sync _|P, 0xffffffff;\nselp.u32 %0, 1, 0, P;\n}" : "=r"(p));
  return p;
}
__device__ __forceinline__ uint32_t set_tag(uint32_t w, uint32_t tag) { uint32_t r; asm("lop3.b32 %0, %1, 0xfffffffe, %2, 0xea;" : "=r"(r) : "r"(w), "r"(tag)); return r; }
__device__ __forceinline__ uint32_t bitsel(uint32_t w, uint32_t m, uint32_t o) { uint32_t r; asm("lop3.b32 %0, %1, %2, %3, 0xe2;" : "=r"(r) : "r"(w), "r"(m), "r"(o)); return r; }
__device__ __forceinline__ uint32_t or3(uint32_t a, uint32_t b, uint32_t c) { uint32_t r; asm("lop3.b32 %0, %1, %2, %3, 0xfe;" : "=r"(r) : "r"(a), "r"(b), "r"(c)); return r; }
__device__ __forceinline__ uint32_t diff2(uint32_t a, uint32_t b, uint32_t tag) { uint32_t r; asm("lop3.b32 %0, %1, %2, %3, 0x7e;" : "=r"(r) : "r"(a), "r"(b), "r"(tag)); return r; }
__device__ __forceinline__ float2 cmul(float2 a, float2 b) { return make_float2(a.x * b.x - a.y * b.y, a.x * b.y + a.y * b.x); }

template<int TB> __device__ __forceinline__ void wgmma_ss_160_0(float (&d)[96], uint32_t al, uint32_t ah, uint32_t bl, uint32_t bh) {
  asm volatile("{\n.reg .b64 da, db;\nmov.b64 da, {%80, %81};\nmov.b64 db, {%82, %83};\n"
    "wgmma.mma_async.sync.aligned.m64n160k16.f32.bf16.bf16 {%0,%1,%2,%3,%4,%5,%6,%7,%8,%9,%10,%11,%12,%13,%14,%15,%16,%17,%18,%19,%20,%21,%22,%23,%24,%25,%26,%27,%28,%29,%30,%31,%32,%33,%34,%35,%36,%37,%38,%39,%40,%41,%42,%43,%44,%45,%46,%47,%48,%49,%50,%51,%52,%53,%54,%55,%56,%57,%58,%59,%60,%61,%62,%63,%64,%65,%66,%67,%68,%69,%70,%71,%72,%73,%74,%75,%76,%77,%78,%79}, da, db, 1, 1, 1, 1, %84;\n}\n"
    : "+f"(d[0]),"+f"(d[1]),"+f"(d[2]),"+f"(d[3]),"+f"(d[4]),"+f"(d[5]),"+f"(d[6]),"+f"(d[7]),"+f"(d[8]),"+f"(d[9]),"+f"(d[10]),"+f"(d[11]),"+f"(d[12]),"+f"(d[13]),"+f"(d[14]),"+f"(d[15]),"+f"(d[16]),"+f"(d[17]),"+f"(d[18]),"+f"(d[19]),"+f"(d[20]),"+f"(d[21]),"+f"(d[22]),"+f"(d[23]),"+f"(d[24]),"+f"(d[25]),"+f"(d[26]),"+f"(d[27]),"+f"(d[28]),"+f"(d[29]),"+f"(d[30]),"+f"(d[31]),"+f"(d[32]),"+f"(d[33]),"+f"(d[34]),"+f"(d[35]),"+f"(d[36]),"+f"(d[37]),"+f"(d[38]),"+f"(d[39]),"+f"(d[40]),"+f"(d[41]),"+f"(d[42]),"+f"(d[43]),"+f"(d[44]),"+f"(d[45]),"+f"(d[46]),"+f"(d[47]),"+f"(d[48]),"+f"(d[49]),"+f"(d[50]),"+f"(d[51]),"+f"(d[52]),"+f"(d[53]),"+f"(d[54]),"+f"(d[55]),"+f"(d[56]),"+f"(d[57]),"+f"(d[58]),"+f"(d[59]),"+f"(d[60]),"+f"(d[61]),"+f"(d[62]),"+f"(d[63]),"+f"(d[64]),"+f"(d[65]),"+f"(d[66]),"+f"(d[67]),"+f"(d[68]),"+f"(d[69]),"+f"(d[70]),"+f"(d[71]),"+f"(d[72]),"+f"(d[73]),"+f"(d[74]),"+f"(d[75]),"+f"(d[76]),"+f"(d[77]),"+f"(d[78]),"+f"(d[79])
    : "r"(al), "r"(ah), "r"(bl), "r"(bh), "n"(TB));
}
template<int TB> __device__ __forceinline__ void wgmma_ss_144_0(float (&d)[96], uint32_t al, uint32_t ah, uint32_t bl, uint32_t bh) {
  asm volatile("{\n.reg .b64 da, db;\nmov.b64 da, {%72, %73};\nmov.b64 db, {%74, %75};\n"
    "wgmma.mma_async.sync.aligned.m64n144k16.f32.bf16.bf16 {%0,%1,%2,%3,%4,%5,%6,%7,%8,%9,%10,%11,%12,%13,%14,%15,%16,%17,%18,%19,%20,%21,%22,%23,%24,%25,%26,%27,%28,%29,%30,%31,%32,%33,%34,%35,%36,%37,%38,%39,%40,%41,%42,%43,%44,%45,%46,%47,%48,%49,%50,%51,%52,%53,%54,%55,%56,%57,%58,%59,%60,%61,%62,%63,%64,%65,%66,%67,%68,%69,%70,%71}, da, db, 1, 1, 1, 1, %76;\n}\n"
    : "+f"(d[0]),"+f"(d[1]),"+f"(d[2]),"+f"(d[3]),"+f"(d[4]),"+f"(d[5]),"+f"(d[6]),"+f"(d[7]),"+f"(d[8]),"+f"(d[9]),"+f"(d[10]),"+f"(d[11]),"+f"(d[12]),"+f"(d[13]),"+f"(d[14]),"+f"(d[15]),"+f"(d[16]),"+f"(d[17]),"+f"(d[18]),"+f"(d[19]),"+f"(d[20]),"+f"(d[21]),"+f"(d[22]),"+f"(d[23]),"+f"(d[24]),"+f"(d[25]),"+f"(d[26]),"+f"(d[27]),"+f"(d[28]),"+f"(d[29]),"+f"(d[30]),"+f"(d[31]),"+f"(d[32]),"+f"(d[33]),"+f"(d[34]),"+f"(d[35]),"+f"(d[36]),"+f"(d[37]),"+f"(d[38]),"+f"(d[39]),"+f"(d[40]),"+f"(d[41]),"+f"(d[42]),"+f"(d[43]),"+f"(d[44]),"+f"(d[45]),"+f"(d[46]),"+f"(d[47]),"+f"(d[48]),"+f"(d[49]),"+f"(d[50]),"+f"(d[51]),"+f"(d[52]),"+f"(d[53]),"+f"(d[54]),"+f"(d[55]),"+f"(d[56]),"+f"(d[57]),"+f"(d[58]),"+f"(d[59]),"+f"(d[60]),"+f"(d[61]),"+f"(d[62]),"+f"(d[63]),"+f"(d[64]),"+f"(d[65]),"+f"(d[66]),"+f"(d[67]),"+f"(d[68]),"+f"(d[69]),"+f"(d[70]),"+f"(d[71])
    : "r"(al), "r"(ah), "r"(bl), "r"(bh), "n"(TB));
}
template<int TB> __device__ __forceinline__ void wgmma_ss_96_0(float (&d)[96], uint32_t al, uint32_t ah, uint32_t bl, uint32_t bh) {
  asm volatile("{\n.reg .b64 da, db;\nmov.b64 da, {%48, %49};\nmov.b64 db, {%50, %51};\n"
    "wgmma.mma_async.sync.aligned.m64n96k16.f32.bf16.bf16 {%0,%1,%2,%3,%4,%5,%6,%7,%8,%9,%10,%11,%12,%13,%14,%15,%16,%17,%18,%19,%20,%21,%22,%23,%24,%25,%26,%27,%28,%29,%30,%31,%32,%33,%34,%35,%36,%37,%38,%39,%40,%41,%42,%43,%44,%45,%46,%47}, da, db, 1, 1, 1, 1, %52;\n}\n"
    : "+f"(d[0]),"+f"(d[1]),"+f"(d[2]),"+f"(d[3]),"+f"(d[4]),"+f"(d[5]),"+f"(d[6]),"+f"(d[7]),"+f"(d[8]),"+f"(d[9]),"+f"(d[10]),"+f"(d[11]),"+f"(d[12]),"+f"(d[13]),"+f"(d[14]),"+f"(d[15]),"+f"(d[16]),"+f"(d[17]),"+f"(d[18]),"+f"(d[19]),"+f"(d[20]),"+f"(d[21]),"+f"(d[22]),"+f"(d[23]),"+f"(d[24]),"+f"(d[25]),"+f"(d[26]),"+f"(d[27]),"+f"(d[28]),"+f"(d[29]),"+f"(d[30]),"+f"(d[31]),"+f"(d[32]),"+f"(d[33]),"+f"(d[34]),"+f"(d[35]),"+f"(d[36]),"+f"(d[37]),"+f"(d[38]),"+f"(d[39]),"+f"(d[40]),"+f"(d[41]),"+f"(d[42]),"+f"(d[43]),"+f"(d[44]),"+f"(d[45]),"+f"(d[46]),"+f"(d[47])
    : "r"(al), "r"(ah), "r"(bl), "r"(bh), "n"(TB));
}
template<int TB> __device__ __forceinline__ void wgmma_ss_96_48(float (&d)[96], uint32_t al, uint32_t ah, uint32_t bl, uint32_t bh) {
  asm volatile("{\n.reg .b64 da, db;\nmov.b64 da, {%48, %49};\nmov.b64 db, {%50, %51};\n"
    "wgmma.mma_async.sync.aligned.m64n96k16.f32.bf16.bf16 {%0,%1,%2,%3,%4,%5,%6,%7,%8,%9,%10,%11,%12,%13,%14,%15,%16,%17,%18,%19,%20,%21,%22,%23,%24,%25,%26,%27,%28,%29,%30,%31,%32,%33,%34,%35,%36,%37,%38,%39,%40,%41,%42,%43,%44,%45,%46,%47}, da, db, 1, 1, 1, 1, %52;\n}\n"
    : "+f"(d[48]),"+f"(d[49]),"+f"(d[50]),"+f"(d[51]),"+f"(d[52]),"+f"(d[53]),"+f"(d[54]),"+f"(d[55]),"+f"(d[56]),"+f"(d[57]),"+f"(d[58]),"+f"(d[59]),"+f"(d[60]),"+f"(d[61]),"+f"(d[62]),"+f"(d[63]),"+f"(d[64]),"+f"(d[65]),"+f"(d[66]),"+f"(d[67]),"+f"(d[68]),"+f"(d[69]),"+f"(d[70]),"+f"(d[71]),"+f"(d[72]),"+f"(d[73]),"+f"(d[74]),"+f"(d[75]),"+f"(d[76]),"+f"(d[77]),"+f"(d[78]),"+f"(d[79]),"+f"(d[80]),"+f"(d[81]),"+f"(d[82]),"+f"(d[83]),"+f"(d[84]),"+f"(d[85]),"+f"(d[86]),"+f"(d[87]),"+f"(d[88]),"+f"(d[89]),"+f"(d[90]),"+f"(d[91]),"+f"(d[92]),"+f"(d[93]),"+f"(d[94]),"+f"(d[95])
    : "r"(al), "r"(ah), "r"(bl), "r"(bh), "n"(TB));
}
__device__ __forceinline__ void wgmma_rs_72(float (&d)[36], uint32_t a0, uint32_t a1, uint32_t a2, uint32_t a3, uint32_t bl, uint32_t bh, int sd) {
  asm volatile("{\n.reg .pred p;\n.reg .b64 db;\nsetp.ne.b32 p, %42, 0;\nmov.b64 db, {%40, %41};\n"
    "wgmma.mma_async.sync.aligned.m64n72k16.f32.bf16.bf16 {%0,%1,%2,%3,%4,%5,%6,%7,%8,%9,%10,%11,%12,%13,%14,%15,%16,%17,%18,%19,%20,%21,%22,%23,%24,%25,%26,%27,%28,%29,%30,%31,%32,%33,%34,%35}, {%36,%37,%38,%39}, db, p, 1, 1, 1;\n}\n"
    : "+f"(d[0]),"+f"(d[1]),"+f"(d[2]),"+f"(d[3]),"+f"(d[4]),"+f"(d[5]),"+f"(d[6]),"+f"(d[7]),"+f"(d[8]),"+f"(d[9]),"+f"(d[10]),"+f"(d[11]),"+f"(d[12]),"+f"(d[13]),"+f"(d[14]),"+f"(d[15]),"+f"(d[16]),"+f"(d[17]),"+f"(d[18]),"+f"(d[19]),"+f"(d[20]),"+f"(d[21]),"+f"(d[22]),"+f"(d[23]),"+f"(d[24]),"+f"(d[25]),"+f"(d[26]),"+f"(d[27]),"+f"(d[28]),"+f"(d[29]),"+f"(d[30]),"+f"(d[31]),"+f"(d[32]),"+f"(d[33]),"+f"(d[34]),"+f"(d[35])
    : "r"(a0), "r"(a1), "r"(a2), "r"(a3), "r"(bl), "r"(bh), "r"(sd));
}
__device__ __forceinline__ void wgmma_rs_48(float (&d)[24], uint32_t a0, uint32_t a1, uint32_t a2, uint32_t a3, uint32_t bl, uint32_t bh, int sd) {
  asm volatile("{\n.reg .pred p;\n.reg .b64 db;\nsetp.ne.b32 p, %30, 0;\nmov.b64 db, {%28, %29};\n"
    "wgmma.mma_async.sync.aligned.m64n48k16.f32.bf16.bf16 {%0,%1,%2,%3,%4,%5,%6,%7,%8,%9,%10,%11,%12,%13,%14,%15,%16,%17,%18,%19,%20,%21,%22,%23}, {%24,%25,%26,%27}, db, p, 1, 1, 1;\n}\n"
    : "+f"(d[0]),"+f"(d[1]),"+f"(d[2]),"+f"(d[3]),"+f"(d[4]),"+f"(d[5]),"+f"(d[6]),"+f"(d[7]),"+f"(d[8]),"+f"(d[9]),"+f"(d[10]),"+f"(d[11]),"+f"(d[12]),"+f"(d[13]),"+f"(d[14]),"+f"(d[15]),"+f"(d[16]),"+f"(d[17]),"+f"(d[18]),"+f"(d[19]),"+f"(d[20]),"+f"(d[21]),"+f"(d[22]),"+f"(d[23])
    : "r"(a0), "r"(a1), "r"(a2), "r"(a3), "r"(bl), "r"(bh), "r"(sd));
}
template<int N,int OFF,int TB> __device__ __forceinline__ void wgmma_ss(float (&d)[96], uint32_t al, uint32_t ah, uint32_t bl, uint32_t bh) {
  if constexpr (N==160 && OFF==0) wgmma_ss_160_0<TB>(d, al, ah, bl, bh);
  else if constexpr (N==144 && OFF==0) wgmma_ss_144_0<TB>(d, al, ah, bl, bh);
  else if constexpr (N==96 && OFF==0) wgmma_ss_96_0<TB>(d, al, ah, bl, bh);
  else if constexpr (N==96 && OFF==48) wgmma_ss_96_48<TB>(d, al, ah, bl, bh);
}

__device__ __forceinline__ void dft3(float2& a, float2& b, float2& c) {
  const float s = 0.86602540378443864676f;
  float2 t = make_float2(b.x + c.x, b.y + c.y), d = make_float2(b.x - c.x, b.y - c.y);
  float2 m = make_float2(fmaf(-0.5f, t.x, a.x), fmaf(-0.5f, t.y, a.y));
  a = make_float2(a.x + t.x, a.y + t.y);
  b = make_float2(fmaf(s, d.y, m.x), fmaf(-s, d.x, m.y));
  c = make_float2(fmaf(-s, d.y, m.x), fmaf(s, d.x, m.y));
}
__device__ __forceinline__ void dft9(float2 (&x)[9]) {
  const float2 w1 = make_float2(0.76604444311897803520f, -0.64278760968653932632f);
  const float2 w2 = make_float2(0.17364817766693034885f, -0.98480775301220805937f);
  const float2 w4 = make_float2(-0.93969262078590838405f, -0.34202014332566873304f);
  dft3(x[0], x[3], x[6]); dft3(x[1], x[4], x[7]); dft3(x[2], x[5], x[8]);
  x[4] = cmul(x[4], w1); x[7] = cmul(x[7], w2); x[5] = cmul(x[5], w2); x[8] = cmul(x[8], w4);
  dft3(x[0], x[1], x[2]); dft3(x[3], x[4], x[5]); dft3(x[6], x[7], x[8]);
  float2 t;
  t = x[1]; x[1] = x[3]; x[3] = t;
  t = x[2]; x[2] = x[6]; x[6] = t;
  t = x[5]; x[5] = x[7]; x[7] = t;
}

__device__ __forceinline__ uint32_t* mod_ptr(Scratch* sc, int u, int t128) {
  const int i = t128 & 15;
  return u < 72 ? sc->moda + (t128 >> 4) * (2 * D_) + 16 * u + 2 * (i & 7) + (i >> 3) : sc->mod + 16 * (u - 72) + i;
}
__device__ __forceinline__ void mod_unit(Scratch* sc, int u, int t128, uint32_t sw_, uint32_t bar, int ph, uint32_t rb, uint32_t tag) {
  const int w = t128 >> 5, l = t128 & 31;
  uint32_t b[18];
#pragma unroll
  for (int i = 0; i < 18; i++) b[i] = lds(red + 512 + (72 * w + 4 * i + (l & 3)) * 4);
  const uint32_t sa = pin(sw_ + (144 * w + (l & 7) + 8 * (l >> 4)) * 32 + (((l >> 3) ^ (l >> 2)) & 1) * 16);
  const uint32_t sr = pin(rb + (l >> 2) * 16 + w * 4);
  uint32_t* const dst = pin(mod_ptr(sc, u, t128));
  const int kind = u / 36;
  const float mul = __uint_as_float(pin(__float_as_uint(kind == 0 ? 16.0f : 1.0f))), add = __uint_as_float(pin(__float_as_uint(kind == 1 || kind == 4 ? 1.0f : 0.0f)));
  mbar_wait(bar, ph);
  if (t128 == 0 && u < 72) TS(10);
  float d[3][4];
#pragma unroll
  for (int i = 0; i < 9; i++) {
    uint32_t a0, a1, a2, a3;
    asm volatile("ldmatrix.sync.aligned.m8n8.x4.trans.shared.b16 {%0,%1,%2,%3}, [%4];" : "=r"(a0), "=r"(a1), "=r"(a2), "=r"(a3) : "r"(sa + i * 512) : "memory");
    if (i < 3) mma16<false>(d[i], a0, a1, a2, a3, b[2 * i], b[2 * i + 1]);
    else mma16<true>(d[i % 3], a0, a1, a2, a3, b[2 * i], b[2 * i + 1]);
  }
  if ((l & 3) == 0) { sts(sr, __float_as_uint(d[0][0] + d[1][0] + d[2][0])); sts(sr + 128, __float_as_uint(d[0][2] + d[1][2] + d[2][2])); }
  bar_sync(4, 128);
  const uint4 v = lds4(rb + (l & 15) * 16);
  const float m = rbf(fmaf(rbf((__uint_as_float(v.x) + __uint_as_float(v.y)) + (__uint_as_float(v.z) + __uint_as_float(v.w))), mul, add));
  if (u < 72 || t128 < 16) *dst = __float_as_uint(m) | tag;
}

__device__ __forceinline__ float rsq(float x) { float r; asm("rsqrt.approx.ftz.f32 %0, %1;" : "=f"(r) : "f"(x)); return r; }
__device__ __forceinline__ void ln_stats2(const float (&a)[18], const float (&b)[18], float sc, float& oa, float& ra, float& ob, float& rb) {
  float v[4] = {0.f, 0.f, 0.f, 0.f}, w[4] = {0.f, 0.f, 0.f, 0.f};
#pragma unroll
  for (int i = 0; i < 18; i += 2) {
    v[0] += a[i]; v[1] = fmaf(a[i], a[i], v[1]); v[2] += b[i]; v[3] = fmaf(b[i], b[i], v[3]);
    w[0] += a[i + 1]; w[1] = fmaf(a[i + 1], a[i + 1], w[1]); w[2] += b[i + 1]; w[3] = fmaf(b[i + 1], b[i + 1], w[3]);
  }
#pragma unroll
  for (int e = 0; e < 4; e++) v[e] += w[e];
#pragma unroll
  for (int o = 16; o; o >>= 1) {
#pragma unroll
    for (int e = 0; e < 4; e++) v[e] += __shfl_xor_sync(0xffffffffu, v[e], o);
  }
  const float ma = v[0] * (1.0f / D_), mb = v[2] * (1.0f / D_);
  ra = sc * rsq(fmaxf(fmaf(-ma, ma, v[1] * (1.0f / D_)), 0.f) + 1e-5f);
  rb = sc * rsq(fmaxf(fmaf(-mb, mb, v[3] * (1.0f / D_)), 0.f) + 1e-5f);
  oa = -ma * ra; ob = -mb * rb;
}

__device__ __forceinline__ void ln_stats1(const float (&a)[18], float sc, float& oa, float& ra) {
  float v[3] = {a[0], a[1], a[2]}, w[3] = {a[0] * a[0], a[1] * a[1], a[2] * a[2]};
#pragma unroll
  for (int i = 3; i < 18; i++) { v[i % 3] += a[i]; w[i % 3] = fmaf(a[i], a[i], w[i % 3]); }
  float s = v[0] + v[1] + v[2], q = w[0] + w[1] + w[2];
#pragma unroll
  for (int o = 16; o; o >>= 1) { s += __shfl_xor_sync(0xffffffffu, s, o); q += __shfl_xor_sync(0xffffffffu, q, o); }
  const float m = s * (1.0f / D_);
  ra = sc * rsq(fmaxf(fmaf(-m, m, q * (1.0f / D_)), 0.f) + 1e-5f);
  oa = -m * ra;
}

__device__ __forceinline__ float tmat(int c, int q, int j) {
  const int ph = q == 1 ? 1024 * j : (q >> 1) * (c + 128 * j) + 512 * (q & 1);
  return __cosf((float)(((ph + 1024) & 2047) - 1024) * (6.283185307179586f / 2048.0f));
}
__device__ __forceinline__ uint32_t line_off(int k1, int kap, int pi, int f) {
  int kd = 64 * k1 + 9 * kap;
  if (kap == 0 && k1 > 4) kd -= 288;
  if (kd >= D_) kd -= D_;
  return pi * 2400 + ((min(kd, D_ - kd) ^ f) << 3);
}

struct Ring { uint32_t st, ph; };
template <bool G2, class T> __device__ __forceinline__ void ring_next(T& st, T& ph) {
  if (++st == NST) st = 0;
  ph ^= ((G2 ? 0xDu : 0x1u) >> st) & 1;
}
__device__ __forceinline__ void arrive_if(uint32_t a, uint32_t p) {
  asm volatile("{\n.reg .pred p;\nsetp.ne.u32 p, %1, 0;\n@p mbarrier.arrive.shared::cta.b64 _, [%0];\n}" ::"r"(a), "r"(p) : "memory");
}
template <int NA> __device__ __forceinline__ void reg_fence_n(float (&d)[96]) {
#pragma unroll
  for (int i = 0; i < NA; i++) asm volatile("" : "+f"(d[i])::"memory");
}
template <int MODE>
__device__ __forceinline__ void gemm_main(float (&acc)[96], uint32_t da0, uint32_t da1, uint32_t db0, int wg, Ring& rg,
                                          bool rows, int J, uint32_t* x1p, const uint32_t (&xr)[18]) {
  constexpr int NKB = MODE == 3 ? 36 : 32;
  constexpr uint32_t HA = 0x40000040u, HB = MODE == 3 ? 0xC0000010u : 0x80000020u;
  constexpr uint32_t KA = 2048 >> 4, KB = (MODE == 3 ? 512 : 1024) >> 4;
  constexpr int NA = MODE == 3 ? 72 : MODE == 1 ? 96 : 80;
  const uint32_t t = threadIdx.x & 127;
  const uint32_t eb = full0 + 8 * NST;
  uint32_t pb = 0, rel = t == 0, prel = 0, ok = 0;
  int n = MODE == 3 ? NKB - J : X1K + 2 * wg;
#pragma unroll 1
  for (int pass = MODE == 3 ? 0 : -1;; pass++) {
#pragma unroll 1
    do {
      const uint32_t so = rg.st * ((MODE == 3 ? STAGE2 : STAGE) >> 4), cb = eb + 8 * rg.st;
      if (__builtin_expect(!ok, 0)) mbar_wait(full0 + 8 * rg.st, rg.ph);
      reg_fence_n<NA>(acc);
      if (MODE == 1 && wg) {
        wg_fence();
#pragma unroll
        for (int k = 0; k < 4; k++) wgmma_ss<96, 48, 1>(acc, da1 + so + k * KA, HA, db0 + so + k * KB, HB);
        wg_commit();
      }
      wg_fence();
#pragma unroll
      for (int k = 0; k < 4; k++) {
        if (k == 3) { ring_next<MODE == 3>(rg.st, rg.ph); ok = PEEK ? mbar_test(full0 + 8 * rg.st, rg.ph) : 0; }
        if (MODE == 0) wgmma_ss<160, 0, 1>(acc, da0 + so + k * KA, HA, db0 + so + k * KB, HB);
        else if (MODE == 3) wgmma_ss<144, 0, 1>(acc, da0 + so + k * KA, HA, db0 + so + k * KB, HB);
        else wgmma_ss<96, 0, 1>(acc, da0 + so + k * KA, HA, db0 + so + k * KB, HB);
      }
      wg_commit();
      wg_wait<1>();
      reg_fence_n<NA>(acc);
      arrive_if(pb, prel);
      pb = cb; prel = rel;
    } while (--n);
    if (pass == 2 - wg) break;
    if (MODE != 3 && pass < 0) {
      if (rows) {
#pragma unroll
        for (int i = 0; i < 9; i++) { x1p[32 * i] = xr[i]; x1p[512 * 288 + 32 * i] = xr[9 + i]; }
      }
      n = NKB - J - X1K - 2 * wg;
      continue;
    }
    n = 1;
    if (pass == 0) {
      if (MODE == 0 && J < NST) prel = rel & wg;
      if (MODE == 3) rel = 0;
      n = J - 1 + wg;
      if (!wg) continue;
      wg_wait<0>();
      arrive_if(pb, prel);
      prel = 0;
    }
    bar_sync(1, 256);
  }
  wg_wait<0>();
  reg_fence_n<NA>(acc);
  if (MODE != 3) arrive_if(pb, prel);
}

constexpr float GK1 = 2.0f * 0.7978845608028654f, GK3 = 8.0f * 0.044715f * 0.7978845608028654f;

__device__ __forceinline__ int kb2_order(int i) { const int wv = i / 6; return 6 * (i - 6 * wv) + ((0x431250 >> (4 * wv)) & 7); }

__device__ __forceinline__ int kb2_pos(int kb) { const int hf = kb >= 36, k = kb - 36 * hf, gr = k / 6; return 64 * hf + gr + 6 * ((0x154230 >> (4 * (k - 6 * gr))) & 7); }

__device__ __forceinline__ void wait_flags(const unsigned* p, int idx, unsigned target, uint32_t& ready) {
  int it = 0;
  while (!((ready >> idx) & 1) && it++ < SPIN_MAX) ready = __ballot_sync(0xffffffffu, (int)(ld_rlx(p) - target) >= 0);
}

enum { B_FULL = 0, B_EMPTY = 6, B_S4 = 12, B_S5, B_LAND, B_FLT = B_LAND + 6, B_Z1, B_Z2, B_GO, B_X, B_WM, B_NUM, B_W0 = B_NUM };

__global__ void __launch_bounds__(NTHR, 1)
fused_kernel(const Params p, const __grid_constant__ Maps maps) {
  extern __shared__ __align__(1024) uint8_t smem_raw[];
  const int bx = blockIdx.x, cta = bx < 112 || bx >= 130 ? bx : bx < 114 ? bx + 16 : bx - 2;
  const int tid = threadIdx.x, t128 = tid & 127;
  const int wp = __shfl_sync(0xffffffffu, tid >> 5, 0), wg = wp >> 2;
  const int l = tid & 31, g = l >> 2, t = l & 3;
  Scratch* const sc = p.s;
  const bool rows = cta < 128;
  const int mu = rows ? cta + 4 : cta - 128;
  const int R = mu - 12;

  uint32_t xr[18];
  uint32_t cv[3];
  const unsigned ep0 = ld_rlx(&sc->cnt[C_EP + l]);
  if (tid == 0) TS(0);
  if (wg == 2) {
#pragma unroll
    for (int i = 0; i < 3; i++) cv[i] = ld_nc(reinterpret_cast<const uint32_t*>(p.c) + min(t128 + 128 * i, 287));
    if (wp == 9 && l < 9 && rows) {
      const int h = 9 * cta + l;
      prefetch_l2(reinterpret_cast<const uint8_t*>(p.wmod) + (size_t)(h >> 1) * (12 * D_) + (h & 1) * (2 * D_), 2 * D_);
    }
    if (tid == 256 && mu < 72) {
      mbar_init(full0 + 8 * B_W0, 1);
      fence_async_smem();
      mbar_expect(full0 + 8 * B_W0, 18432);
#pragma unroll 1
      for (int i = 0; i < 3; i++) tma2d(sbase + O_P2 + i * 6144, &maps.wm, 16 * mu, 192 * i, full0 + 8 * B_W0);
    }
    __syncwarp();
#pragma unroll 1
    for (int u = mu < 72 ? mu : 72 + mu; u < 216; u += u < 72 ? 72 : NCTA) if (u < 72 || t128 < 16) *mod_ptr(sc, u, t128) = 0;
    if (wp == 11 && smem_u32(smem_raw) != sbase) __trap();
    if (wp >= 10 && elect()) {
#pragma unroll 1
      for (int i = wp - 10; i < B_NUM; i += 2) mbar_init(full0 + 8 * i, i == B_FLT ? 4 : i == B_WM ? 3 : i < B_S4 ? 2 : 1);
      fence_async_smem();
    }
    __syncwarp();
  } else if (rows) {
    const uint32_t* xs = reinterpret_cast<const uint32_t*>(p.x) + (size_t)(cta + 128 * ((wp & 3) + 8 * wg)) * 288 + l;
#pragma unroll
    for (int i = 0; i < 9; i++) { xr[i] = ld_nc(xs + 32 * i); xr[9 + i] = ld_nc(xs + 512 * 288 + 32 * i); }
  }
  CK(0);
  if (tid == 64 && cta == NCTA - 1) prefetch_l2(p.tab, sizeof(T_TAB));
  __syncwarp();
  auto tag_of = [](unsigned e) { return (e & 0x7fffu) | 0x8000u; };
  const int kap = 8 * ((wp & 3) ^ (wg & 1)) + g;
  uint32_t tb[4], sb1[3], lo[9];
#pragma unroll
  for (int i = 0; i < 4; i++) tb[i] = pin(pack_bf16(tmat(cta, 8 * (i >> 1) + g, t + 8 * (i & 1)), tmat(cta, 8 * (i >> 1) + g, t + 8 * (i & 1) + 4)));
#pragma unroll
  for (int i = 0; i < 3; i++) {
    const int d = 48 * wp + 16 * i + (l & 15);
    sb1[i] = pin(sbase + O_B1 + (l >> 4) * 9216 + (d % 9) * 1024 + (d & 63) * 16);
  }
#pragma unroll
  for (int k1 = 0; k1 < 9; k1++) lo[k1] = pin(sbase + O_Z1 + line_off(k1, kap, 4 * wg + t, cta & 3));
  const uint32_t snt = pin(sbase + O_NRM + ((l & 7) + 8 * (l >> 4)) * 1168 + (48 * wp + (l & 8)) * 2), sn = pin(sbase + O_NRM + wp * 2336 + l * 4);
  const uint32_t smask = pin(t ? 0u : 0xffff0000u);
  const uint32_t* const mp = pin(sc->moda + (cta >> 4) * (2 * D_) + 48 * wp + 2 * g);
  const uint4* const ftab = pin(p.tab + TB_F + (t128 ^ (wg << 5)));

  if (wg == 2) {
#pragma unroll
    for (int i = 0; i < 3; i++) {
      const float c0 = bf_lo(cv[i]), c1 = bf_hi(cv[i]);
      sts(red + 512 + min(t128 + 128 * i, 287) * 4, pack_bf16(__fdividef(c0, 1.0f + __expf(-c0)), __fdividef(c1, 1.0f + __expf(-c1))));
    }
    if (t128 == 0) sts(full0 + 248, ep0 + 1);
    if (wp == 9 && l < 11) asm volatile("prefetch.tensormap [%0];" ::"l"(&maps.z1 + l) : "memory");
    bar_sync(4, 128);
    if (mu < 72) {
      mod_unit(sc, mu, t128, sbase + O_P2, full0 + 8 * B_W0, 0, red, tag_of(upin(ep0) + 1));
      if (t128 == 0) TS(25);
    }
    CK(1);
  }
  const int pi = R / 15, col0 = 20 * (R - 15 * pi);
  const int xu = DF_ * pi + col0, xv = DF_ * (pi ? 16 - pi : 8) + col0;
  auto load_filter = [&](int a) {
    const int x = (a & 1) ? xv : xu;
    const bool wide = (x & 15) > 12;
    mbar_expect(full0 + 8 * B_FLT, wide ? 12288 : 8192);
    tma2d(sbase + O_RAW + a * 12288, &maps.wf[a & 2], x & ~15, 0, full0 + 8 * B_FLT);
    if (wide) tma2d(sbase + O_RAW + a * 12288 + 8192, &maps.wf[(a & 2) + 1], (x & ~15) + 32, 0, full0 + 8 * B_FLT);
  };
  uint4 af[4];
  if (rows) {
    uint2 ms[3], mc[3];
    auto load_mod = [&](uint32_t o = 0) {
#pragma unroll
      for (int i = 0; i < 3; i++) { ms[i] = ld_rlx2(mp + 2 * o + 16 * i); mc[i] = ld_rlx2(mp + 2 * o + D_ + 16 * i); }
    };
    if (wg < 2) {
      float a[18], b[18];
#pragma unroll
      for (int i = 0; i < 9; i++) { a[2 * i] = bf_lo(xr[i]); a[2 * i + 1] = bf_hi(xr[i]); b[2 * i] = bf_lo(xr[9 + i]); b[2 * i + 1] = bf_hi(xr[9 + i]); }
      float oa, ra, ob, rb;
      ln_stats2(a, b, 1.0f, oa, ra, ob, rb);
      CK(1);
      load_mod((__float_as_uint(ra) | __float_as_uint(rb)) >> 31);
#pragma unroll
      for (int i = 0; i < 9; i++) {
        sts(sn + i * 128, pack_bf16(fmaf(a[2 * i], ra, oa), fmaf(a[2 * i + 1], ra, oa)));
        sts(sn + 1168 + i * 128, pack_bf16(fmaf(b[2 * i], rb, ob), fmaf(b[2 * i + 1], rb, ob)));
      }
      CK(2);
      bar_arrive(10, NTHR);
#pragma unroll
      for (int kk = 0; kk < 4; kk++) af[kk] = ld_nc4(ftab + kk * 128);
      bar_sync(1, 256);
      if (tid == 0) TS(2);
    } else {
      bar_sync(10, NTHR);
      load_mod();
      CK(2);
      if (wp >= 10 && elect()) prefetch_l2(reinterpret_cast<const uint8_t*>(wp == 10 ? p.wr : p.wi) + cta * 9248, 9248);
      __syncwarp();
    }
    float rs[3][8];
#pragma unroll
    for (int i = 0; i < 3; i++) {
      uint32_t a0, a1, a2, a3;
      asm volatile("ldmatrix.sync.aligned.m8n8.x4.trans.shared.b16 {%0,%1,%2,%3}, [%4];" : "=r"(a0), "=r"(a1), "=r"(a2), "=r"(a3)
                   : "r"(snt + 32 * i) : "memory");
      mma16<false>(&rs[i][0], a0, a1, a2, a3, tb[0], tb[1]);
      mma16<false>(&rs[i][4], a0, a1, a2, a3, tb[2], tb[3]);
    }
    CK(3);
    const uint32_t tag16 = tag_of(upin(ep0) + 1), tag1 = tag16 & 1;
    {
      int it = 0;
#pragma unroll 1
      while (true) {
        uint32_t bad = 0;
#pragma unroll
        for (int i = 0; i < 3; i++) bad |= diff2(ms[i].x, ms[i].y, tag16) | diff2(mc[i].x, mc[i].y, tag16);
        if (!any(bad & 0xffffu) || ++it > SPIN_MAX) break;
        load_mod();
      }
      CK(4);
      if (tid == 0) TS(3);
#pragma unroll
      for (int i = 0; i < 3; i++) {
        const float c0 = bf_hi(mc[i].x), c1 = bf_hi(mc[i].y);
        const float s0 = __uint_as_float(ms[i].x & smask), s1 = __uint_as_float(ms[i].y & smask);
        stmatrix4(sb1[i], pack_bf16(fmaf(rs[i][0], c0, s0), rs[i][1] * c0), pack_bf16(fmaf(rs[i][2], c1, s1), rs[i][3] * c1),
                  pack_bf16(rs[i][4] * c0, rs[i][5] * c0), pack_bf16(rs[i][6] * c1, rs[i][7] * c1));
      }
    }
    fence_async_smem();
    CK(5);
    if (wg == 2) {
      bar_arrive(5, NTHR);
      if (R >= 0 && elect()) load_filter(wp - 8);
      __syncwarp();
      const int slot = 4 * (cta & 7) + ((cta >> 4) & 3) + 32 * (2 * (cta >> 6) + ((cta >> 3) & 1));
      const uint32_t c0 = upin(40 * slot), c1 = upin(60 * (wp & 1)), src = upin(sbase + O_Z1 + (wp & 1) * 9600);
      const CUtensorMap* mz = upin(&maps.z1);
      unsigned* hint = pin(sc->cnt + C_Z1 + 32 * (wp & 1));
      if (wp < 10) {
        bar_sync(2 + (wp & 1), 160);
        if (elect()) tma_st2d(mz, src, c0, c1);
        pause(HD1);
        if (elect()) red_add(hint, 1);
        bulk_commit_wait();
        if (tid == 256) TS(4);
        __syncwarp();
      }
    } else {
      bar_sync(5, NTHR);
      CK(6);
      float acc[36];
      const uint32_t db = (((sbase + O_B1 + wg * 9216) & 0x3FFFF) >> 4) | ((128 >> 4) << 16);
      wg_fence();
#pragma unroll
      for (int kk = 0; kk < 4; kk++) wgmma_rs_72(acc, af[kk].x, af[kk].y, af[kk].z, af[kk].w, db + kk * 16, 1024 >> 4, kk);
      wg_commit();
      wg_wait<0>();
      reg_fence(acc);
      CK(7);
      float2 za[9], zb[9];
#pragma unroll
      for (int i = 0; i < 9; i++) { za[i] = make_float2(acc[4 * i], acc[4 * i + 2]); zb[i] = make_float2(acc[4 * i + 1], acc[4 * i + 3]); }
      dft9(za); dft9(zb);
      if ((wp & 3) == wg) {
        const float sp = g ? 0.f : 1.f;
#pragma unroll
        for (int k = 1; k < 5; k++) {
          float2 a = za[k], b = za[9 - k];
          za[k] = make_float2(fmaf(sp, b.x, a.x), fmaf(-sp, b.y, a.y)); za[9 - k] = make_float2(fmaf(-sp, a.x, b.x), fmaf(sp, a.y, b.y));
          a = zb[k]; b = zb[9 - k];
          zb[k] = make_float2(fmaf(sp, b.x, a.x), fmaf(-sp, b.y, a.y)); zb[9 - k] = make_float2(fmaf(-sp, a.x, b.x), fmaf(sp, a.y, b.y));
        }
        const uint32_t w0 = set_tag(pack_bf16(za[0].y, 0.f), tag1), w1 = pack_bf16(zb[0].y, 0.f);
        asm volatile("{\n.reg .pred p;\nsetp.eq.u32 p, %3, 0;\n@p st.shared.v2.b32 [%0], {%1,%2};\n}" ::"r"(lo[0] + 288 * 8), "r"(w0), "r"(w1), "r"(g) : "memory");
        za[0].y = g ? za[0].y : 0.f; zb[0].y = g ? zb[0].y : 0.f;
      }
#pragma unroll
      for (int k1 = 0; k1 < 9; k1++) sts2(lo[k1], set_tag(pack_bf16(za[k1].x, za[k1].y), tag1), pack_bf16(zb[k1].x, zb[k1].y));
      fence_async_smem();
      CK(8);
      bar_arrive(2 + wg, 160);
      {
        const uint32_t fx = (((cta >> 4) ^ cta) & 3) << 3, dl = O_IN - O_Z1, st = sbase + O_ST + 15360 + tid * 16;
        sts4(st, (lo[0] ^ fx) + dl, (lo[1] ^ fx) + dl, (lo[2] ^ fx) + dl, (lo[3] ^ fx) + dl);
        sts4(st + 4096, (lo[4] ^ fx) + dl, (lo[5] ^ fx) + dl, (lo[6] ^ fx) + dl, (lo[7] ^ fx) + dl);
        sts4(st + 8192, (lo[8] ^ fx) + dl, (lo[0] ^ fx) + dl + (kap ? 0 : 288 * 8),
             sbase + O_B3 + wg * 1024 + (l >> 4) * 2048 + (2 * (kap & 24) + (l & 15)) * 16, 0);
      }
    }
    {
      uint32_t sy[6];
#pragma unroll
      for (int i = 0; i < 6; i++) {
        const int rr = 16 * (wp & 3) + g + 8 * (i & 1);
        sy[i] = sbase + O_Y + (t * 584 + 64 * ((3 * wg + (i >> 1) + 63 - rr) % 9) + rr) * 4;
      }
      sts4(sbase + O_ST + tid * 16, movm(tb[0]), movm(tb[2]), movm(tb[1]), movm(tb[3]));
      sts4(sbase + O_ST + 6144 + tid * 16, sy[0], sy[1], sy[2], sy[3]);
      sts2(sbase + O_ST + 12288 + tid * 8, sy[4], sy[5]);
    }
  } else {
    __syncthreads();
  }

  const unsigned ep = upin(lds(full0 + 248));
  const uint32_t tag16 = tag_of(ep), tag1 = ep & 1;
  auto load_wm = [&](int u) {
    if (wp > 8 && elect()) {
      mbar_expect(full0 + 8 * B_WM, 6144);
      tma2d(sbase + O_NRM + (wp - 9) * 6144, &maps.wm, 16 * u, 192 * (wp - 9), full0 + 8 * B_WM);
    }
    __syncwarp();
  };
  if (R >= 0) {
    const int nl = (col0 + wp < DF_) + (wg < 2 && col0 + wp + 12 < DF_);
    uint4 cf[2][4], G[4];
#pragma unroll
    for (int i = 0; i < 4; i++) {
      cf[0][i] = __ldg(p.tab + TB_P2 + i * 32 + l);
      cf[1][i] = __ldg(p.tab + TB_P2 + (pi ? i : 4 + i) * 32 + l);
      G[i] = __ldg(p.tab + TB_P2 + (8 + i) * 32 + l);
    }
    const uint32_t* zin = sc->z1 + (size_t)R * 5120;
    if (wp == 10) {
      const uint32_t* zu = upin(zin);
      if (elect()) mbar_expect(full0 + 8 * B_Z1, 20480);
      wait_cnt(sc->cnt + C_Z1 + 32 * (pi >> 2), 128 * ep - 40 * STRESS);
      if (elect()) {
        bulk_ld(sbase + O_P2, zu, 20480, full0 + 8 * B_Z1);
        TS(12);
      }
      __syncwarp();
    }
    mbar_wait(full0 + 8 * B_FLT, 0);
    CK(9);
    float wn[16], wc[16];
#pragma unroll 1
    for (int ln = nl - 1; ln >= 0; ln--) {
      const int col = col0 + wp + 12 * ln, k2 = (57 * col) & 63;
      const bool cj = k2 > 32;
      const float nr = ((col & 31) == 0 && col != 0 && col != 288 ? 0.5f : 1.0f) / ((float)S_ * D_), ni = cj ? -nr : nr;
#pragma unroll
      for (int i = 0; i < 16; i++) wn[i] = wc[i];
#pragma unroll
      for (int cl = 0; cl < 2; cl++) {
        const int v = cl ^ (cj && pi), e = ((v ? xv : xu) & 15) + wp + 12 * ln, sh = e < 32 ? 6 : 5;
        const uint32_t base = sbase + O_RAW + v * 12288 + (e < 32 ? 2 * e : 8192 - 64 + 2 * e), msk = e < 32 ? 0x30 : 0x10;
        const int dm = v ? (cj || pi ? -1 : 0) : 0;
#pragma unroll
        for (int tt = 0; tt < 4; tt++) {
          const int kc = g + 64 * (tt >> 1) + 16 * t + 8 * (tt & 1);
          uint32_t a = base + ((((cj ? -kc : kc) + dm) & 127) << sh);
          a ^= (a >> 3) & msk;
          wc[4 * tt + 2 * cl] = lds_bf(a) * nr; wc[4 * tt + 2 * cl + 1] = lds_bf(a + 24576) * ni;
        }
      }
    }
    const float al = __uint_as_float(pin((pi ? 0x3f800000u : 0u) + (l >> 5)));
    const uint32_t tagv = pin(tag1 + (l >> 5));
    CK(10);
    uint32_t off = pin(l * 160 + ((wp ^ (g & 3)) << 3));
    uint32_t offo = pin(sbase + O_P2 + 20480 + off - 64 * l), po = 3072;
    unsigned* hz2 = pin(sc->cnt + C_Z2);
    const uint32_t do2 = pin(12288 - 32 * l);
    const CUtensorMap* mz2 = upin(&maps.z2[wp == 0]);
    const uint32_t sz2 = upin(sbase + O_P2 + 20480 + (wp ? 0 : 12288)), cz2 = upin(40 * R + (wp ? 0 : 24));
    mbar_wait(full0 + 8 * B_Z1, 0);
    CK(11);
    if (tid == 0) TS(8);
    if (wg == 2) load_wm(72 + mu);
    uint2 v[4], v2[4];
    const uint32_t o2 = nl > 1 ? 96 : 0;
#pragma unroll
    for (int i = 0; i < 4; i++) { v[i] = lds2(sbase + O_P2 + off + i * 5120); v2[i] = lds2(sbase + O_P2 + off + o2 + i * 5120); }
    auto bad2 = [&]() {
      return any(or3(or3(diff2(v[0].x, v[1].x, tagv), diff2(v[2].x, v[3].x, tagv), diff2(v2[0].x, v2[1].x, tagv)), diff2(v2[2].x, v2[3].x, tagv), 0) & 1);
    };
    if (__builtin_expect(bad2() && nl, 0)) {
      FAILCNT(0);
      int it = 0;
      do {
#pragma unroll
        for (int i = 0; i < 4; i++) {
          v[i] = ld_rlx2(reinterpret_cast<const uint8_t*>(zin) + off + i * 5120);
          v2[i] = ld_rlx2(reinterpret_cast<const uint8_t*>(zin) + off + o2 + i * 5120);
        }
      } while (bad2() && ++it < SPIN_MAX);
    }
#pragma unroll 1
    for (int ln = 0; ln < nl; ln++, offo += do2, po = 2048) {
      float d[4][4];
      uint32_t A[8];
#pragma unroll
      for (int h = 0; h < 2; h++) {
        mma16<false>(d[2 * h], cf[0][0].x, cf[0][0].y, cf[0][0].z, cf[0][0].w, v[h].x, v[2 + h].x);
        mma16<false>(d[2 * h + 1], cf[1][0].x, cf[1][0].y, cf[1][0].z, cf[1][0].w, v[h].y, v[2 + h].y);
      }
      if (ln) { fence_async_smem(); bar_arrive(15, NTHR); }
#pragma unroll
      for (int h = 0; h < 2; h++)
#pragma unroll
        for (int L = 0; L < 2; L++) {
          const uint4 tw = cf[L][2 + h];
          const float* z = d[2 * h + L];
          const float2 z0 = cmul(make_float2(z[0], z[2]), make_float2(__uint_as_float(tw.x), __uint_as_float(tw.y)));
          const float2 z1 = cmul(make_float2(z[1], z[3]), make_float2(__uint_as_float(tw.z), __uint_as_float(tw.w)));
          A[4 * h + L] = pack_bf16(z0.x, z0.y); A[4 * h + 2 + L] = pack_bf16(z1.x, z1.y);
        }
#pragma unroll
      for (int tt = 0; tt < 4; tt++) {
        mma16<false>(d[tt], A[0], A[1], A[2], A[3], G[tt].x, G[tt].y);
        mma16<true>(d[tt], A[4], A[5], A[6], A[7], G[tt].z, G[tt].w);
      }
#pragma unroll
      for (int tt = 0; tt < 4; tt++) {
        const float ar = d[tt][0], aj = d[tt][1], br = d[tt][2], bj = d[tt][3];
        const float2 y1 = cmul(make_float2(fmaf(-al, bj, ar), fmaf(al, br, aj)), make_float2(wc[4 * tt], wc[4 * tt + 1]));
        const float2 y2 = cmul(make_float2(fmaf(al, ar, bj), fmaf(al, aj, -br)), make_float2(wc[4 * tt + 2], wc[4 * tt + 3]));
        A[2 * tt] = pack_bf16(fmaf(al, y2.x, y1.x), fmaf(-al, y2.y, -y1.y));
        A[2 * tt + 1] = pack_bf16(fmaf(al, y1.y, -y2.y), fmaf(al, y1.x, -y2.x));
      }
#pragma unroll
      for (int i = 0; i < 16; i++) wc[i] = wn[i];
#pragma unroll
      for (int i = 0; i < 4; i++) v[i] = v2[i];
#pragma unroll
      for (int tt = 0; tt < 4; tt++) {
        mma16<false>(d[tt], A[0], A[1], A[2], A[3], G[tt].x, G[tt].y);
        mma16<true>(d[tt], A[4], A[5], A[6], A[7], G[tt].z, G[tt].w);
      }
#pragma unroll
      for (int h = 0; h < 2; h++)
#pragma unroll
        for (int L = 0; L < 2; L++) {
          const uint4 tw = cf[L][2 + h];
          const float2 z0 = cmul(make_float2(d[2 * h][2 * L], d[2 * h][2 * L + 1]), make_float2(__uint_as_float(tw.x), __uint_as_float(tw.y)));
          const float2 z1 = cmul(make_float2(d[2 * h + 1][2 * L], d[2 * h + 1][2 * L + 1]), make_float2(__uint_as_float(tw.z), __uint_as_float(tw.w)));
          A[4 * h + 2 * L] = movm(pack_bf16(z0.x, z1.x)); A[4 * h + 2 * L + 1] = movm(pack_bf16(z0.y, z1.y));
        }
#pragma unroll
      for (int h = 0; h < 2; h++) {
        mma16<false>(d[0], cf[0][1].x, cf[0][1].y, cf[0][1].z, cf[0][1].w, A[4 * h], A[4 * h + 1]);
        mma16<false>(d[1], cf[1][1].x, cf[1][1].y, cf[1][1].z, cf[1][1].w, A[4 * h + 2], A[4 * h + 3]);
#pragma unroll
        for (int e = 0; e < 2; e++)
          sts2(offo + (2 * h + e) * po, set_tag(pack_bf16(d[0][e], d[0][2 + e]), tagv), pack_bf16(d[1][e], d[1][2 + e]));
      }
      CK(12 + ln);
    }
    if (tid == 0) TS(1);
    fence_async_smem();
    if (nl < 2 && wp != 8) bar_arrive(15, NTHR);
    if (wp) bar_arrive(6, NTHR);
    if (!(wp & 7)) {
      bar_sync(wp ? 15 : 6, NTHR);
      if (elect()) tma_st2d(mz2, sz2, cz2, 0);
      if (wp == 0 && elect()) red_add(hz2, 1);
      if (tid == 0) TS(9);
      if (wp == 0) bulk_commit_wait();
      __syncwarp();
    }
  }
  if (wg == 2) {
#pragma unroll 1
    for (int u = 72 + mu, k = 0; u < 216; u += NCTA, k ^= 1) {
      if (R < 0) { fence_async_smem(); bar_sync(4, 128); load_wm(u); }
      mod_unit(sc, u, t128, sbase + O_NRM, full0 + 8 * B_WM, k, red + 256 - 256 * k, tag16);
    }
    fence_async_smem();
    CK(13);
  }

  const int grp = bx / 11, m1 = bx - 11 * grp;
  const bool helper = (m1 & 3) == 3;
  const int f1 = 384 * grp + (helper ? 192 : 128) * (m1 >> 2);
  const int d1 = 160 * (m1 & 3), flip = m1 >= 7;
  const int a1bytes = helper ? 24576 : 16384;
  auto load_a1 = [&](int st, int kb) {
    mbar_expect(full0 + 8 * st, a1bytes);
    tma4d_ef(sbase + st * STAGE, helper ? &maps.w1b : &maps.w1a, 4 * (kb >> 3), 16 * (kb & 7), f1 >> 6, full0 + 8 * st);
  };

  uint32_t bia[4];
  if (wg < 2) {
    const int fa = f1 + (helper ? 128 : 64) * (wg ^ flip) + 16 * (wp & 3) + g, fb = helper ? f1 + 64 + 16 * (wp & 3) + g : fa;
#pragma unroll
    for (int i = 0; i < 4; i++) asm volatile("ld.global.nc.u16 %0, [%1];" : "=r"(bia[i]) : "l"(p.b1 + (i < 2 ? fa : fb) + 8 * (i & 1)) : "memory");
  }
  if (rows) {
#pragma unroll
    for (int kk = 0; kk < 4; kk++) af[kk] = __ldg(p.tab + TB_E + kk * 128 + t128);
    const uint4 c0 = lds4(sbase + O_ST + tid * 16), c1 = lds4(sbase + O_ST + 6144 + tid * 16);
    const uint2 c2 = lds2(sbase + O_ST + 12288 + tid * 8);
    const uint32_t tc[4] = {c0.x, c0.y, c0.z, c0.w}, sy[6] = {c1.x, c1.y, c1.z, c1.w, c2.x, c2.y};
    const uint32_t l8 = pin(8 * l), syl = pin(sbase + O_Y + wp * 2336 + 8 * l);
    uint32_t sh3[3], ham[3];
#pragma unroll
    for (int k = 0; k < 3; k++) {
      const int pos = k && (l >> 4) == k - 1 ? 2 * (l & 6) + ((l >> 2) & 2) + (l & 1) : l & 15;
      const int sw = 2 * cta + ((wp >> 1) & 1), ph = pos ^ ((sw & 3) << 2);
      sh3[k] = pin((l >> 4) * 256 + (wp & 3) * 64 + ph * 4);
      ham[k] = pin(((ph ^ sw) & 7) == 0 ? ~1u : ~0u);
    }
    unsigned* const hh3 = upin(sc->cnt + C_H3 + (cta >> 4));
    uint8_t* const h3g = pin(sc->h3 + (cta >> 4) * (18 * 4096) + (cta & 15) * 256 + (l >> 4) * 3840);
    const int slot = 4 * (cta >> 4) + ((cta >> 1) & 3) + 32 * (2 * ((cta >> 3) & 1) + (cta & 1));
    const uint32_t* zin = sc->z2 + (size_t)slot * 4800;
    if (wg == 2) {
      {
        uint4 v[4];
        const int i3 = min(t128 + 384, 431);
        int it = 0;
        while (true) {
          uint32_t bad = 0;
#pragma unroll
          for (int k = 0; k < 4; k++) v[k] = ld_rlx4(sc->mod + 4 * (k < 3 ? t128 + 128 * k : i3));
#pragma unroll
          for (int k = 0; k < 4; k++) {
            v[k].x ^= tag16; v[k].y ^= tag16; v[k].z ^= tag16; v[k].w ^= tag16;
            bad |= v[k].x | v[k].y | v[k].z | v[k].w;
          }
          if (!any(bad & 0xffffu) || ++it > SPIN_MAX) break;
        }
#pragma unroll
        for (int k = 0; k < 4; k++) sts4(sbase + O_MOD + 16 * (k < 3 ? t128 + 128 * k : i3), v[k].x, v[k].y, v[k].z, v[k].w);
      }
      CK(14);
      bulk_commit_wait();
      bar_sync(10, NTHR);
      mbar_wait(full0 + 8 * B_Z2, 0);
      if (elect()) {
        load_a1(wp - 8, wp - 8);
      }
      __syncwarp();
    } else {
      const uint4 e0 = lds4(sbase + O_ST + 15360 + tid * 16), e1 = lds4(sbase + O_ST + 19456 + tid * 16), e2 = lds4(sbase + O_ST + 23552 + tid * 16);
      const uint32_t li[9] = {e0.x, e0.y, e0.z, e0.w, e1.x, e1.y, e1.z, e1.w, e2.x}, lx = e2.y, sb3 = e2.z;
      bar_arrive(10, NTHR);
      CK(14);
      if (wp == 1) {
        const uint32_t* zu = upin(zin);
        if (elect()) mbar_expect(full0 + 8 * B_Z2, 19200);
        wait_cnt(sc->cnt + C_Z2, 120 * ep - 40 * STRESS);
        if (elect()) {
          bulk_ld(sbase + O_IN, zu, 19200, full0 + 8 * B_Z2);
          TS(14);
        }
        __syncwarp();
      }
      mbar_wait(full0 + 8 * B_Z2, 0);
      CK(15);
      if (tid == 0) TS(11);
      uint2 v[10];
#pragma unroll
      for (int k1 = 0; k1 < 10; k1++) v[k1] = lds2(k1 < 9 ? li[k1] : lx);
      float2 za[9], zb[9];
      int it = 0;
#pragma unroll 1
      while (true) {
      const uint32_t bad = or3(or3(diff2(v[0].x, v[1].x, tag1), diff2(v[2].x, v[3].x, tag1), diff2(v[4].x, v[5].x, tag1)), diff2(v[6].x, v[7].x, tag1), diff2(v[8].x, v[9].x, tag1));
#pragma unroll
      for (int i = 0; i < 9; i++) { za[i] = make_float2(bf_lo(v[i].x), bf_hi(v[i].x)); zb[i] = make_float2(bf_lo(v[i].y), bf_hi(v[i].y)); }
      if ((wp & 3) == wg) {
        const float sp = g ? 0.f : 1.f;
#pragma unroll
        for (int k = 1; k < 5; k++) {
          float2 a = za[k], b = za[9 - k];
          za[k] = make_float2(fmaf(-sp, b.x, a.x), fmaf(sp, b.y, a.y)); za[9 - k] = make_float2(fmaf(sp, a.x, b.x), fmaf(-sp, a.y, b.y));
          a = zb[k]; b = zb[9 - k];
          zb[k] = make_float2(fmaf(-sp, b.x, a.x), fmaf(sp, b.y, a.y)); zb[9 - k] = make_float2(fmaf(sp, a.x, b.x), fmaf(-sp, a.y, b.y));
        }
        za[0].y = g ? za[0].y : bf_lo(v[9].x); zb[0].y = g ? zb[0].y : bf_lo(v[9].y);
      }
      dft9(za); dft9(zb);
#pragma unroll
      for (int n = 0; n < 8; n += 2) {
        const int i0 = (9 - n) % 9, i1 = 8 - n;
        stmatrix4(sb3 + n * 2048, pack_bf16(za[i0].x, zb[i0].x), pack_bf16(za[i0].y, zb[i0].y), pack_bf16(za[i1].x, zb[i1].x), pack_bf16(za[i1].y, zb[i1].y));
      }
      stmatrix2(sb3 + 8 * 2048, pack_bf16(za[1].x, zb[1].x), pack_bf16(za[1].y, zb[1].y));
      if (__builtin_expect(!any(bad & 1) || ++it > SPIN_MAX, 1)) break;
      FAILCNT(1);
#pragma unroll
      for (int k1 = 0; k1 < 10; k1++) v[k1] = ld_rlx2(reinterpret_cast<const uint8_t*>(zin) + (pin(k1 < 9 ? li[k1] : lx) - (sbase + O_IN)));
      }
      fence_async_smem();
    }
    CK(16);
    __syncthreads();
    CK(17);
    float acc[24];
    const uint32_t db = (((sbase + O_B3 + wg * 6144) & 0x3FFFF) >> 4) | ((128 >> 4) << 16);
    wg_fence();
#pragma unroll
    for (int kk = 0; kk < 4; kk++) wgmma_rs_48(acc, af[kk].x, af[kk].y, af[kk].z, af[kk].w, db + kk * 16, 1024 >> 4, kk);
    wg_commit();
    uint32_t ga[9];
    if (wg < 2) {
#pragma unroll
      for (int i = 0; i < 9; i++) { const uint2 v = lds2(l8 + sbase + O_MOD + 256 * i); ga[i] = __byte_perm(v.x, v.y, 0x7632); }
    }
    wg_wait<0>();
    reg_fence(acc);
    CK(18);
#pragma unroll
    for (int i = 0; i < 3; i++) {
      const float* a = &acc[8 * i];
      const uint32_t a0 = pack_bf16(a[0], a[1]), a1 = pack_bf16(a[2], a[3]), a2 = pack_bf16(a[4], a[5]), a3 = pack_bf16(a[6], a[7]);
#pragma unroll
      for (int jh = 0; jh < 2; jh++) {
        float y[4];
        mma16<false>(y, a0, a1, a2, a3, tc[2 * jh], tc[2 * jh + 1]);
        sts(sy[2 * i] + jh * (4 * 584 * 4), pack_bf16(y[0], y[1]));
        sts(sy[2 * i + 1] + jh * (4 * 584 * 4), pack_bf16(y[2], y[3]));
      }
    }
    CK(19);
    if (wg == 2) bar_arrive(7, NTHR); else bar_sync(7, NTHR);
    if (wg) bar_sync(15, NTHR);
    if (wg < 2) {
      CK(20);
      uint2 y[9], sh[9], sw[9];
#pragma unroll
      for (int i = 0; i < 9; i++) y[i] = lds2(syl + 256 * i);
      uint32_t sel = 0x5410, sto = sbase + O_B3 + wg * 9216;
#pragma unroll 1
      for (int e = 0; e < 2; e++, sel = 0x7632, sto += 4608) {
        float a[18];
#pragma unroll
        for (int i = 0; i < 9; i++) {
          const uint32_t x1 = hfma2(ga[i], __byte_perm(y[i].x, y[i].y, sel), xr[i]);
          xr[i] = xr[9 + i]; xr[9 + i] = x1;
          a[2 * i] = bf_lo(x1); a[2 * i + 1] = bf_hi(x1);
        }
#pragma unroll
        for (int i = 0; i < 9; i++) { lds2_if(!e, sh[i], l8 + sbase + O_MOD + 4 * D_ + 256 * i); lds2_if(!e, sw[i], l8 + sbase + O_MOD + 8 * D_ + 256 * i); }
        float oa, ra;
        ln_stats1(a, 1.0f, oa, ra);
#pragma unroll
        for (int i = 0; i < 9; i++) {
          a[2 * i] = fmaf(fmaf(a[2 * i], ra, oa), __uint_as_float(sw[i].x), __uint_as_float(sh[i].x));
          a[2 * i + 1] = fmaf(fmaf(a[2 * i + 1], ra, oa), __uint_as_float(sw[i].y), __uint_as_float(sh[i].y));
        }
        ln_stats1(a, 0.5f, oa, ra);
        uint32_t hv[9];
#pragma unroll
        for (int i = 0; i < 9; i++) hv[i] = bitsel(pack_bf16(fmaf(a[2 * i], ra, oa), fmaf(a[2 * i + 1], ra, oa)), ham[i == 2 ? 1 : i == 6 ? 2 : 0], tag1);
        if (!(wg | e)) {
          if (elect()) red_add(hh3, 1);
#pragma unroll
          for (int i = 0; i < 9; i++) asm volatile("st.global.b32 [%0], %1;" ::"l"(h3g + sh3[i == 2 ? 1 : i == 6 ? 2 : 0] + i * 8192), "r"(hv[i]) : "memory");
          bar_arrive(15, NTHR);
          if (tid == 0) TS(13);
        } else {
#pragma unroll
          for (int i = 0; i < 9; i++) sts(sto + sh3[i == 2 ? 1 : i == 6 ? 2 : 0] + i * 512, hv[i]);
        }
        if (!e) bar_arrive(8, 288);
        CK(21 + e);
      }
      fence_async_smem();
      bar_arrive(9, 288);
      CK(23);
    }
  }

  const bool g2 = rows;
  const int z2 = cta, r = z2 >> 6;
  const int s2 = 128 * ((z2 >> 2) & 15), d2 = 144 * (z2 & 3);
  constexpr int ST0 = 32 % NST;
  const bool first = helper || m1 < W0N;

  if (wg == 2) {
    asm volatile("setmaxnreg.dec.sync.aligned.u32 40;");
    auto load_b = [&](bool second, int i, int st) {
      const uint32_t lb = full0 + 8 * (B_LAND + st), bytes = second ? 18432 : STAGE - a1bytes;
      mbar_expect(lb, bytes);
      bulk_ld(sbase + (second ? st * STAGE2 + 16384 : st * STAGE + a1bytes),
              second ? sc->u + ((size_t)(36 * r + kb2_order(i)) * D_ + d2) * 128 : sc->h3 + ((size_t)(i * 18 + (d1 >> 5)) << 12), bytes, lb);
    };
    if (wp == 8) {
      int st = rows ? 4 : 0, ph = 1;
#pragma unroll 1
      for (int kb = st; kb < 32; kb++) {
        if (rows && (kb >> 1) == 2) mbar_wait(full0 + 8 * (B_S4 - 4 + kb), 0);
        mbar_wait(empty0 + 8 * st, ph);
        if (elect()) {
          load_a1(st, kb);
        }
        __syncwarp();
        ring_next<false>(st, ph);
      }
      if (g2) {
        st++;
#pragma unroll 1
        for (int i = 0; i < 36; i++) {
          if (i == HOLDA) mbar_wait(full0 + 8 * B_GO, 0);
          mbar_wait(empty0 + 8 * st, ph);
          if (elect()) {
            mbar_expect(full0 + 8 * st, 16384);
            tma3d_ef(sbase + st * STAGE2, &maps.w2, 64 * (36 * r + kb2_order(i)), s2 >> 6, full0 + 8 * st);
          }
          __syncwarp();
          ring_next<true>(st, ph);
        }
      }
    } else if (wp >= 10) {
      const int sw = wp - 10;
      if (sw) {
        if (rows) {
          bar_sync(8, 288);
          mbar_wait(full0 + 8 * H3W, 0);
          if (elect()) mbar_arrive(full0 + 8 * B_S4);
          bar_sync(9, 288);
          if (elect()) tma_st3d(&maps.h3, sbase + O_B3 + 4608, 64 * (cta & 15), 18 * (cta >> 4), 1);
          bulk_commit_wait();
          if (elect()) {
            red_add(sc->cnt + C_H3 + (cta >> 4) + 8, 4);
            mbar_arrive(full0 + 8 * B_S5);
            TS(24);
            asm volatile("fence.acq_rel.gpu;" ::: "memory");
            red_add(&sc->cnt[C_X + 64], 1);
          }
          __syncwarp();
        }
        if (g2) {
          uint2 v[3];
          int it = 0;
          do {
#pragma unroll
            for (int i = 0; i < 3; i++) v[i] = ld_rlx2(sc->mod + 3 * D_ + d2 + 2 * min(l + 32 * i, 71));
          } while (any(or3(diff2(v[0].x, v[0].y, tag16), diff2(v[1].x, v[1].y, tag16), diff2(v[2].x, v[2].y, tag16)) & 0xffffu) && ++it < SPIN_MAX);
#pragma unroll
          for (int i = 0; i < 3; i++) sts(sbase + O_GB + 4 * min(l + 32 * i, 71), __byte_perm(v[i].x, v[i].y, 0x7632));
          __syncwarp();
        }
        wait_cnt<true>(&sc->cnt[C_X + 64], 128 * ep);
        if (elect()) mbar_arrive(full0 + 8 * B_X);
        __syncwarp();
      }
      uint32_t lph = 0;
      auto check_tiles = [&](bool second, int n, int st, uint32_t o1, uint32_t d2nd) {
        const uint32_t b1 = pin(sbase + o1), b2 = pin(sbase + o1 + d2nd);
        int i = 0, it = 0;
#pragma unroll 1
        do {
          const uint32_t so = st * (second ? STAGE2 : STAGE);
          mbar_wait(full0 + 8 * (B_LAND + st), (lph >> st) & 1);
          lph ^= 1u << st;
          uint32_t v[20];
#pragma unroll
          for (int k = 0; k < 20; k++) if (!second || k < 10 || k >= 12) v[k] = lds(k < 12 ? b1 + so + k * 1024 : b2 + so + (k - 12) * 1024); else v[k] = tag1;
#pragma unroll
          for (int k = 0; k < 10; k++) v[k] = diff2(v[2 * k], v[2 * k + 1], tag1);
          const uint32_t bad = or3(or3(or3(v[0], v[1], v[2]), or3(v[3], v[4], v[5]), v[6]), v[7], or3(v[8], v[9], 0));
          if (__builtin_expect(any(bad & 1) && ++it < SPIN_MAX, 0)) {
            FAILCNT(2 + second);
            fence_async_smem();
            __syncwarp();
            if (elect()) load_b(second, i, st);
            __syncwarp();
            continue;
          }
          if (elect()) mbar_arrive(full0 + 8 * st);
          if (++st == NST) st = 0;
          i++;
        } while (i < n);
      };
      if (!sw) check_tiles(false, NV1, 0, a1bytes + l * 32 + (l >> 2) * 4, helper ? 4096 : 12288);
      if (sw) {
#pragma unroll 1
        for (int k = 0; k < 2; k++) {
          bar_sync(13 + k, 160);
          if (helper || (first && !k)) continue;
          const uint32_t stg = sbase + (k ? O_U1 : ST0 * STAGE);
          const int kb = (f1 >> 6) + (k ^ flip);
          uint8_t* const ug = sc->u + ((size_t)kb * D_ + d1) * 128;
          if (g2) mbar_wait(full0 + 8 * B_GO, 0);
          if (first) pause(10 * TRK0);
#pragma unroll 1
          for (int i = 0; i < 20480; i += 2048) {
            if (elect()) bulk_st(ug + i, stg + i, 2048);
            pause(k ? TRKC : TRK0);
          }
          if (elect()) red_add(sc->cnt + C_U + kb2_pos(kb), 4);
          bulk_commit_wait();
          if (elect()) { if (!k) mbar_arrive(empty0 + 8 * ST0); TS(k ? 23 : 17); }
          __syncwarp();
        }
        if (elect()) { asm volatile("fence.acq_rel.gpu;" ::: "memory"); red_add(&sc->cnt[C_X], 1); }
        __syncwarp();
      }
      if (g2) {
        if (!sw) check_tiles(true, NV2, 3, 16384 + l * 32 + g * 4, 10240);
        else {
          wait_cnt<true>(&sc->cnt[C_X], NCTA * ep);
          if (elect()) mbar_arrive(full0 + 8 * B_X);
          if (cta == 0) sc->cnt[C_EP + (pin(l) ^ 1)] = ep;
          __syncwarp();
        }
      }
      __syncwarp();
    } else {
      uint32_t ready = 0;
      int st = 0, ph = 1;
#pragma unroll 1
      for (int kb = 0; kb < 32; kb++) {
        const uint8_t* src = upin(sc->h3 + ((size_t)(kb * 18 + (d1 >> 5)) << 12));
        const uint32_t dst = upin(sbase + st * STAGE + a1bytes), lb = full0 + 8 * ((kb < NV1 ? B_LAND : 0) + st);
        if (kb == NV1) { mbar_wait(full0 + 8 * B_X, 0); fence_async_glb(); ready = ~0u; }
        if (rows && (kb >> 1) == 2) mbar_wait(full0 + 8 * (B_S4 - 4 + kb), 0);
        mbar_wait(empty0 + 8 * st, ph);
        if (elect()) mbar_expect(lb, STAGE - a1bytes);
        wait_flags(sc->cnt + C_H3 + l, (kb & 7) + (kb < 8 ? 0 : 8), 64 * ep - 24 * STRESS, ready);
        if (elect()) bulk_ld(dst, src, STAGE - a1bytes, lb);
        ring_next<false>(st, ph);
      }
      if (g2) {
        ready = 0;
        st++;
#pragma unroll 1
        for (int i = 0; i < 36; i++) {
          const int kb = kb2_order(i);
          const uint8_t* src = upin(sc->u + ((size_t)(36 * r + kb) * D_ + d2) * 128);
          const uint32_t dst = upin(sbase + st * STAGE2 + 16384), lb = full0 + 8 * ((i < NV2 ? B_LAND : 0) + st);
          if (i == NV2) { mbar_wait(full0 + 8 * B_X, 1); fence_async_glb(); ready = ~0u; }
          mbar_wait(empty0 + 8 * st, ph);
          if (elect()) mbar_expect(lb, 18432);
          wait_flags(sc->cnt + C_U + 64 * r + l, i & 31, 16 * ep - 8 * STRESS, ready);
          if (elect()) {
            bulk_ld(dst, src, 18432, lb);
            if (i == GOAT) mbar_arrive(full0 + 8 * B_GO);
          }
          ring_next<true>(st, ph);
        }
      }
    }
  } else {
    asm volatile("setmaxnreg.inc.sync.aligned.u32 232;");
    const int wgu = wg;
    constexpr uint32_t sb4 = sbase >> 4;
    const int w = wp & 3;
    Ring rg = {0, 0};
    uint32_t* const x1p = p.out + (size_t)(cta + 128 * ((wp & 3) + 8 * wg)) * 288 + l;
    const int direct = helper || (first && !wg), kbA = (f1 >> 6) + (helper ? 2 : 1) * (wg ^ flip), kbB = (f1 >> 6) + 1;
    const uint32_t uo = (t >> 1) * 2048 + (16 * w + g) * 32 + (((t ^ (g >> 2)) & 1) << 4);
    const uint32_t ad = pin(sbase + (wg ? O_U1 : ST0 * STAGE) + uo);
    uint8_t* const ug0 = pin(sc->u + ((size_t)kbA * D_ + d1) * 128 + uo);
    const int ud1 = upin(helper ? (kbB - kbA) * (D_ * 128) - 3 * 4096 : 0);
    unsigned* const uh = pin(sc->cnt + C_U + kb2_pos(l ? kbB : kbA));
    const int eh = direct && !helper && !l;
    const bool utg = ((t ^ (g >> 2) ^ w) & 1) == 0;
    const uint32_t um0 = pin(utg && g < 4 ? ~1u : ~0u), um1 = pin(utg && g >= 4 ? ~1u : ~0u);
    float acc[96];
    constexpr uint32_t LA = (8192 >> 4) << 16, LB = (4096 >> 4) << 16;
    {
      const float a0 = 0.5f * bf_lo(pin(bia[0])), a1 = 0.5f * bf_lo(pin(bia[1])), b0 = 0.5f * bf_lo(pin(bia[2])), b1 = 0.5f * bf_lo(pin(bia[3]));
#pragma unroll
      for (int i = 0; i < 96; i++) acc[i] = i < 48 ? ((i & 2) ? a1 : a0) : ((i & 2) ? b1 : b0);
      reg_fence(acc);
    }
    if (!helper) gemm_main<0>(acc, sb4 + (wgu ^ flip) * 512 + LA, 0, sb4 + 1024 + LB, wgu, rg, rows, first ? NST : NST - 1, x1p, xr);
    else {
      float ac2[96];
#pragma unroll
      for (int i = 0; i < 96; i++) asm volatile("mov.b32 %0, %1;" : "=f"(ac2[i]) : "f"(acc[i]));
      gemm_main<1>(ac2, sb4 + (wgu ^ flip) * 1024 + LA, sb4 + 512 + LA, sb4 + 1536 + LB, wgu, rg, rows, NST - 1, x1p, xr);
#pragma unroll
      for (int i = 0; i < 96; i++) asm volatile("mov.b32 %0, %1;" : "=f"(acc[i]) : "f"(ac2[i]));
    }
    if (t128 == 0) { TS(wg ? 16 : 6); if (wg) TSC(5); }
    {
      float tp[2] = {0.f, 0.f};
#pragma unroll
      for (int j = 0; j < 12; j++) {
        const float* a = &acc[16 * (j >> 1) + 2 * (j & 1)];
        const float k3 = j < 2 ? (GV ? GK1 : GK3) : fmaf(tp[j & 1], 0.0f, GV ? GK1 : GK3);
        uint32_t o[4];
#pragma unroll
        for (int e = 0; e < 4; e++) {
          const float h0 = a[4 * e], h1 = a[4 * e + 1];
          float z0 = GV ? h0 * fmaf(h0 * h0, GK3, k3) : h0 * fmaf(h0 * k3, h0, GK1), z1 = GV ? h1 * fmaf(h1 * h1, GK3, k3) : h1 * fmaf(h1 * k3, h1, GK1);
          asm("tanh.approx.f32 %0, %0;" : "+f"(z0));
          asm("tanh.approx.f32 %0, %0;" : "+f"(z1));
          if (e == GDEP) tp[j & 1] = z0;
          o[e] = pack_bf16(fmaf(h0, z0, h0), fmaf(h1, z1, h1));
          if ((e >> 1) == (j & 1)) o[e] = bitsel(o[e], (e & 1) ? um1 : um0, tag1);
        }
        if (EH && j == EH) asm volatile("{\n.reg .pred p;\nsetp.ne.u32 p, %1, 0;\n@p red.relaxed.gpu.global.add.u32 [%0], 1;\n}" ::"l"(uh), "r"(eh) : "memory");
        asm volatile("{\n.reg .pred p;\nsetp.ne.u32 p, %6, 0;\n@p st.global.v4.b32 [%0], {%2,%3,%4,%5};\n@!p st.shared.v4.b32 [%1], {%2,%3,%4,%5};\n}"
                     ::"l"(ug0 + (j < 6 ? 0 : ud1) + (j >> 1) * 4096 + (j & 1) * 256), "r"(ad + (j >> 1) * 4096 + (j & 1) * 256),
                       "r"(o[0]), "r"(o[1]), "r"(o[2]), "r"(o[3]), "r"(direct) : "memory");
        if ((j == 5 && helper && !wgu) || (j == 9 && !helper)) break;
      }
      if (!direct) fence_async_smem();
      else if (l <= wgu && (EH == 0 || helper)) red_add(uh, 1);
      __syncwarp();
      bar_arrive(13 + wgu, 160);
      if (t128 == 0) TS(wg ? 29 : 28);
    }
    if (g2) {
      const int mb = wgu ^ r;
      const int odd = z2 & 1;
      uint4 gq[4];
      uint2 gs;
      {
        float a0 = 0.f, a1 = 0.f;
        if (wgu) { a0 = __bfloat162float(p.b2[s2 + 64 * mb + 16 * w + g]); a1 = __bfloat162float(p.b2[s2 + 64 * mb + 16 * w + 8 + g]); }
#pragma unroll
        for (int i = 0; i < 4; i++) gq[i] = lds4(sbase + O_GB + 32 * odd + 64 * i + 16 * t);
        gs = lds2(sbase + O_GB + (odd ? 0 : 256) + 8 * t);
#pragma unroll
        for (int i = 0; i < 72; i++) acc[i] = (i & 2) ? a1 : a0;
      }
      uint32_t* const ob = p.out + (size_t)(s2 + 64 * mb + 16 * w + g) * 288 + (d2 >> 1);
      uint32_t* const oq = pin(ob + 8 * odd + 4 * t);
      uint32_t* const os = pin(ob + (odd ? 0 : 64) + 2 * t);
      rg.st++;
      gemm_main<3>(acc, sb4 + mb * 512 + LA, 0, sb4 + 1024 + ((2048 >> 4) << 16), wgu, rg, rows, NST, x1p, xr);
      if (t128 == 0) { TS(wg ? 20 : 19); if (wg) TSC(22); }
      auto finish = [&](const float* aq, const float* as) {
#pragma unroll
        for (int i = 0; i < 8; i++) {
          const float* a = aq + 16 * (i >> 1) + 2 * (i & 1);
          const uint4 gv = gq[i >> 1];
          red_bf16x8(oq + (i & 1) * 2304 + 16 * (i >> 1), hmul2(gv.x, pack_bf16(a[0], a[1])), hmul2(gv.y, pack_bf16(a[4], a[5])),
                     hmul2(gv.z, pack_bf16(a[8], a[9])), hmul2(gv.w, pack_bf16(a[12], a[13])));
        }
#pragma unroll
        for (int i = 0; i < 2; i++) red_bf16x4(os + i * 2304, hmul2(gs.x, pack_bf16(as[2 * i], as[2 * i + 1])), hmul2(gs.y, pack_bf16(as[2 * i + 4], as[2 * i + 5])));
      };
      if (odd) finish(&acc[8], &acc[0]); else finish(&acc[0], &acc[64]);
      if (t128 == 0) TS(wg ? 7 : 21);
      __syncwarp();
    }
  }
}

typedef CUresult (*EncodeFn)(CUtensorMap*, CUtensorMapDataType, cuuint32_t, void*, const cuuint64_t*, const cuuint64_t*, const cuuint32_t*,
                             const cuuint32_t*, CUtensorMapInterleave, CUtensorMapSwizzle, CUtensorMapL2promotion, CUtensorMapFloatOOBfill);

struct Dim { cuuint64_t n, stride; cuuint32_t box; };
template <int RANK>
void make_map(EncodeFn enc, CUtensorMap* m, bool words, int swz, const void* ptr, const Dim (&d)[RANK]) {
  cuuint64_t gd[RANK], gs[RANK];
  cuuint32_t bx[RANK], es[RANK];
  for (int i = 0; i < RANK; i++) { gd[i] = d[i].n; gs[i] = d[i].stride; bx[i] = d[i].box; es[i] = 1; }
  enc(m, words ? CU_TENSOR_MAP_DATA_TYPE_UINT32 : CU_TENSOR_MAP_DATA_TYPE_BFLOAT16, RANK, const_cast<void*>(ptr), gd, gs + 1, bx, es,
      CU_TENSOR_MAP_INTERLEAVE_NONE, static_cast<CUtensorMapSwizzle>(swz),
      swz == 3 ? CU_TENSOR_MAP_L2_PROMOTION_L2_256B : CU_TENSOR_MAP_L2_PROMOTION_NONE, CU_TENSOR_MAP_FLOAT_OOB_FILL_NONE);
}

}

extern "C" void kernel_launch(void* const* d_in, const int* in_sizes, int n_in, void* d_out, int out_size) {
  (void)in_sizes; (void)n_in; (void)out_size;
  static EncodeFn enc = nullptr;
  static void *sptr = nullptr, *tptr = nullptr;
  if (!enc) {
    void* f = nullptr; cudaDriverEntryPointQueryResult qr;
    cudaGetDriverEntryPoint("cuTensorMapEncodeTiled", &f, cudaEnableDefault, &qr);
    enc = reinterpret_cast<EncodeFn>(f);
    cudaFuncSetAttribute(fused_kernel, cudaFuncAttributeMaxDynamicSharedMemorySize, SMEM_BYTES);
    cudaGetSymbolAddress(&sptr, g_s);
    cudaGetSymbolAddress(&tptr, T_TAB);
  }
  Params p;
  p.x = (const __nv_bfloat16*)d_in[0]; p.wr = (const __nv_bfloat16*)d_in[1]; p.wi = (const __nv_bfloat16*)d_in[2];
  p.b1 = (const __nv_bfloat16*)d_in[5]; p.b2 = (const __nv_bfloat16*)d_in[7];
  p.c = (const __nv_bfloat16*)d_in[8]; p.wmod = (const __nv_bfloat16*)d_in[9];
  p.w1 = (const __nv_bfloat16*)d_in[4]; p.w2 = (const __nv_bfloat16*)d_in[6];
  p.out = static_cast<uint32_t*>(d_out); p.s = static_cast<Scratch*>(sptr); p.tab = static_cast<const uint4*>(tptr);
  Maps maps;
  make_map<4>(enc, &maps.w1a, false, 3, p.w1, {{64, 0, 64}, {16, 128 * 2 * F_, 4}, {128, 2 * F_, 16}, {72, 128, 2}});
  make_map<4>(enc, &maps.w1b, false, 3, p.w1, {{64, 0, 64}, {16, 128 * 2 * F_, 4}, {128, 2 * F_, 16}, {72, 128, 3}});
  make_map<3>(enc, &maps.w2, false, 3, p.w2, {{64, 0, 64}, {F_, 2 * S_, 64}, {32, 128, 2}});
  make_map<2>(enc, &maps.z1, true, 0, p.s->z1, {{5120, 0, 40}, {120, 20480, 60}});
  for (int i = 0; i < 2; i++) make_map<2>(enc, &maps.z2[i], true, 0, p.s->z2, {{4800, 0, i ? 16u : 24u}, {128, 19200, 128}});
  for (int i = 0; i < 4; i++) make_map<2>(enc, &maps.wf[i], false, 2 - (i & 1), (i & 2) ? p.wi : p.wr, {{16 * DF_, 0, (i & 1) ? 16u : 32u}, {128, 32 * DF_, 128}});
  make_map<2>(enc, &maps.wm, false, 1, p.wmod, {{6 * D_, 0, 16}, {D_, 12 * D_, 192}});
  make_map<3>(enc, &maps.h3, true, 0, p.s->h3, {{1024, 0, 64}, {144, 4096, 18}, {4, 144 * 4096, 3}});
  fused_kernel<<<NCTA, NTHR, SMEM_BYTES, cudaStreamPerThread>>>(p, maps);
}
```

```cpp
#include <cuda_runtime.h>
#include <cuda_bf16.h>
#include <cuda.h>
#include <stdint.h>

namespace {

constexpr int S_ = 2048, D_ = 576, DF_ = 289, F_ = 4608;
constexpr int NCTA = 132, NTHR = 384;
constexpr int STAGE = 36864, NST = 6;
constexpr int STAGE2 = 34816, O_U1 = NST * STAGE2, O_GB = O_U1 + 20480, SMEM_BYTES = 232448;
constexpr uint32_t sbase = 1024, red = sbase + NST * STAGE, full0 = sbase + SMEM_BYTES - 256, empty0 = full0 + 8 * NST;
constexpr int O_NRM = 0, O_B1 = 19456, O_Z1 = 38912, O_P2 = 59392, O_ST = 3 * STAGE;
constexpr int O_RAW = 4 * STAGE;
constexpr int O_IN = 4 * STAGE, O_Y = O_IN + 19456, O_B3 = O_IN + 38912, O_MOD = O_IN + 57344;

__device__ __align__(128) const uint32_t T_TAB[5632] = {
0x3f803f80,0xbf803f80,0x3f803f80,0xbf803f80,0x3f803f80,0xbf803f80,0x3f803f80,0xbf803f80,0x3f803f80,0xbf803f80,0x3f803f80,0xbf803f80,
0x3f803f80,0xbf803f80,0x3f803f80,0xbf803f80,0x3f7f3f80,0xbdc90000,0x3f223f35,0xbf46bf35,0x3f753f7b,0xbe95be48,0x3ef13f0e,0xbf62bf55,
0x3f623f6d,0xbef1bec4,0x3e953ec4,0xbf75bf6d,0x3f463f55,0xbf22bf0e,0x3dc93e48,0xbf7fbf7b,0x3f7b3f80,0xbe480000,0xbe480000,0xbf7bbf80,
0x3f553f6d,0xbf0ebec4,0xbf0ebec4,0xbf55bf6d,0x3f0e3f35,0xbf55bf35,0xbf55bf35,0xbf0ebf35,0x3e483ec4,0xbf7bbf6d,0xbf7bbf6d,0xbe48bec4,
0x3f753f80,0xbe950000,0xbf62bf35,0xbef1bf35,0x3f223f55,0xbf46bf0e,0xbf7fbf7b,0x3dc9be48,0x3dc93ec4,0xbf7fbf6d,0xbf46bf6d,0x3f223ec4,
0xbef1be48,0xbf62bf7b,0xbe95bf0e,0x3f753f55,0x3f6d3f80,0xbec40000,0xbf6dbf80,0x3ec40000,0x3ec43f35,0xbf6dbf35,0xbec4bf35,0x3f6d3f35,
0xbec40000,0xbf6dbf80,0x3ec40000,0x3f6d3f80,0xbf6dbf35,0xbec4bf35,0x3f6d3f35,0x3ec43f35,0x3f623f80,0xbef10000,0xbe95bf35,0x3f753f35,
0x3dc93f0e,0xbf7fbf55,0x3f223e48,0x3f463f7b,0xbf46bec4,0xbf22bf6d,0x3f7f3f6d,0xbdc93ec4,0xbf75bf7b,0x3e95be48,0x3ef13f55,0xbf62bf0e,
0x3f553f80,0xbf0e0000,0x3f0e0000,0x3f553f80,0xbe483ec4,0xbf7bbf6d,0x3f7b3f6d,0xbe483ec4,0xbf7bbf35,0xbe48bf35,0x3e483f35,0xbf7bbf35,
0xbf0ebf6d,0x3f553ec4,0xbf55bec4,0xbf0ebf6d,0x3f463f80,0xbf220000,0x3f7f3f35,0x3dc93f35,0xbef13e48,0xbf62bf7b,0x3e953f55,0xbf75bf0e,
0xbf75bf6d,0x3e95bec4,0xbf62bec4,0xbef1bf6d,0x3dc9bf0e,0x3f7f3f55,0xbf22bf7b,0x3f463e48,0x3f353f80,0xbf350000,0x3f353f80,0xbf350000,
0xbf350000,0xbf35bf80,0xbf350000,0xbf35bf80,0xbf35bf80,0x3f350000,0xbf35bf80,0x3f350000,0x3f350000,0x3f353f80,0x3f350000,0x3f353f80,
0x3f223f80,0xbf460000,0xbdc93f35,0xbf7fbf35,0xbf62be48,0xbef1bf7b,0xbf75bf55,0x3e95bf0e,0xbe95bf6d,0x3f753ec4,0x3ef1bec4,0x3f623f6d,
0x3f7f3f0e,0x3dc93f55,0x3f463f7b,0xbf223e48,0x3f0e3f80,0xbf550000,0xbf550000,0xbf0ebf80,0xbf7bbec4,0xbe48bf6d,0xbe48bf6d,0x3f7b3ec4,
0x3e48bf35,0x3f7b3f35,0x3f7b3f35,0xbe483f35,0x3f553f6d,0xbf0e3ec4,0xbf0e3ec4,0xbf55bf6d,0x3ef13f80,0xbf620000,0xbf75bf35,0x3e95bf35,
0xbf7fbf0e,0x3dc9bf55,0x3f46be48,0x3f223f7b,0x3f22bec4,0x3f463f6d,0x3dc93f6d,0xbf7fbec4,0x3e953f7b,0xbf75be48,0xbf62bf55,0x3ef1bf0e,
0x3ec43f80,0xbf6d0000,0xbec4bf80,0x3f6d0000,0xbf6dbf35,0x3ec4bf35,0x3f6d3f35,0xbec43f35,0x3f6d0000,0x3ec43f80,0xbf6d0000,0xbec4bf80,
0xbec43f35,0xbf6dbf35,0x3ec4bf35,0x3f6d3f35,0x3e953f80,0xbf750000,0x3ef1bf35,0x3f623f35,0xbf46bf55,0x3f22bf0e,0x3dc93f7b,0xbf7fbe48,
0x3f7f3ec4,0xbdc93f6d,0xbf22bf6d,0x3f46bec4,0xbf623e48,0xbef1bf7b,0x3f753f0e,0xbe953f55,0x3e483f80,0xbf7b0000,0x3f7b0000,0x3e483f80,
0xbf0ebf6d,0x3f55bec4,0xbf553ec4,0xbf0ebf6d,0x3f553f35,0xbf0e3f35,0x3f0ebf35,0x3f553f35,0xbf7bbec4,0x3e48bf6d,0xbe483f6d,0xbf7bbec4,
0x3dc93f80,0xbf7f0000,0x3f463f35,0xbf223f35,0xbe95bf7b,0x3f75be48,0xbf62bf0e,0x3ef1bf55,0x3ef13f6d,0xbf623ec4,0x3f753ec4,0xbe953f6d,
0xbf22bf55,0x3f46bf0e,0xbf7fbe48,0x3dc9bf7b,0x3f80,0xbf800000,0x3f80,0xbf800000,0xbf80,0x3f800000,0xbf80,0x3f800000,
0x3f80,0xbf800000,0x3f80,0xbf800000,0xbf80,0x3f800000,0xbf80,0x3f800000,0xbdc93f80,0xbf7f0000,0xbf463f35,0xbf22bf35,
0x3e95bf7b,0x3f753e48,0x3f62bf0e,0x3ef13f55,0xbef13f6d,0xbf62bec4,0xbf753ec4,0xbe95bf6d,0x3f22bf55,0x3f463f0e,0x3f7fbe48,0x3dc93f7b,
0xbe483f80,0xbf7b0000,0xbf7b0000,0x3e48bf80,0x3f0ebf6d,0x3f553ec4,0x3f553ec4,0xbf0e3f6d,0xbf553f35,0xbf0ebf35,0xbf0ebf35,0x3f55bf35,
0x3f7bbec4,0x3e483f6d,0x3e483f6d,0xbf7b3ec4,0xbe953f80,0xbf750000,0xbef1bf35,0x3f62bf35,0x3f46bf55,0x3f223f0e,0xbdc93f7b,0xbf7f3e48,
0xbf7f3ec4,0xbdc9bf6d,0x3f22bf6d,0x3f463ec4,0x3f623e48,0xbef13f7b,0xbf753f0e,0xbe95bf55,0xbec43f80,0xbf6d0000,0x3ec4bf80,0x3f6d0000,
0x3f6dbf35,0x3ec43f35,0xbf6d3f35,0xbec4bf35,0xbf6d0000,0x3ec4bf80,0x3f6d0000,0xbec43f80,0x3ec43f35,0xbf6d3f35,0xbec4bf35,0x3f6dbf35,
0xbef13f80,0xbf620000,0x3f75bf35,0x3e953f35,0x3f7fbf0e,0x3dc93f55,0xbf46be48,0x3f22bf7b,0xbf22bec4,0x3f46bf6d,0xbdc93f6d,0xbf7f3ec4,
0xbe953f7b,0xbf753e48,0x3f62bf55,0x3ef13f0e,0xbf0e3f80,0xbf550000,0x3f550000,0xbf0e3f80,0x3f7bbec4,0xbe483f6d,0x3e48bf6d,0x3f7bbec4,
0xbe48bf35,0x3f7bbf35,0xbf7b3f35,0xbe48bf35,0xbf553f6d,0xbf0ebec4,0x3f0e3ec4,0xbf553f6d,0xbf223f80,0xbf460000,0x3dc93f35,0xbf7f3f35,
0x3f62be48,0xbef13f7b,0x3f75bf55,0x3e953f0e,0x3e95bf6d,0x3f75bec4,0xbef1bec4,0x3f62bf6d,0xbf7f3f0e,0x3dc9bf55,0xbf463f7b,0xbf22be48,
0xbf353f80,0xbf350000,0xbf353f80,0xbf350000,0x3f350000,0xbf353f80,0x3f350000,0xbf353f80,0x3f35bf80,0x3f350000,0x3f35bf80,0x3f350000,
0xbf350000,0x3f35bf80,0xbf350000,0x3f35bf80,0xbf463f80,0xbf220000,0xbf7f3f35,0x3dc9bf35,0x3ef13e48,0xbf623f7b,0xbe953f55,0xbf753f0e,
0x3f75bf6d,0x3e953ec4,0x3f62bec4,0xbef13f6d,0xbdc9bf0e,0x3f7fbf55,0x3f22bf7b,0x3f46be48,0xbf553f80,0xbf0e0000,0xbf0e0000,0x3f55bf80,
0x3e483ec4,0xbf7b3f6d,0xbf7b3f6d,0xbe48bec4,0x3f7bbf35,0xbe483f35,0xbe483f35,0xbf7b3f35,0x3f0ebf6d,0x3f55bec4,0x3f55bec4,0xbf0e3f6d,
0xbf623f80,0xbef10000,0x3e95bf35,0x3f75bf35,0xbdc93f0e,0xbf7f3f55,0xbf223e48,0x3f46bf7b,0x3f46bec4,0xbf223f6d,0xbf7f3f6d,0xbdc9bec4,
0x3f75bf7b,0x3e953e48,0xbef13f55,0xbf623f0e,0xbf6d3f80,0xbec40000,0x3f6dbf80,0x3ec40000,0xbec43f35,0xbf6d3f35,0x3ec4bf35,0x3f6dbf35,
0x3ec40000,0xbf6d3f80,0xbec40000,0x3f6dbf80,0x3f6dbf35,0xbec43f35,0xbf6d3f35,0x3ec4bf35,0xbf753f80,0xbe950000,0x3f62bf35,0xbef13f35,
0xbf223f55,0xbf463f0e,0x3f7fbf7b,0x3dc93e48,0xbdc93ec4,0xbf7f3f6d,0x3f46bf6d,0x3f22bec4,0x3ef1be48,0xbf623f7b,0x3e95bf0e,0x3f75bf55,
0xbf7b3f80,0xbe480000,0x3e480000,0xbf7b3f80,0xbf553f6d,0xbf0e3ec4,0x3f0ebec4,0xbf553f6d,0xbf0e3f35,0xbf553f35,0x3f55bf35,0xbf0e3f35,
0xbe483ec4,0xbf7b3f6d,0x3f7bbf6d,0xbe483ec4,0xbf7f3f80,0xbdc90000,0xbf223f35,0xbf463f35,0xbf753f7b,0xbe953e48,0xbef13f0e,0xbf623f55,
0xbf623f6d,0xbef13ec4,0xbe953ec4,0xbf753f6d,0xbf463f55,0xbf223f0e,0xbdc93e48,0xbf7f3f7b,0x3f803f80,0xbf803f80,0x3f803f80,0xbf803f80,
0x3f803f80,0xbf803f80,0x3f803f80,0xbf803f80,0x3f803f80,0xbf803f80,0x3f803f80,0xbf803f80,0x3f803f80,0xbf803f80,0x3f803f80,0xbf803f80,
0xbdc90000,0xbf7fbf80,0xbf46bf35,0xbf22bf35,0xbe95be48,0xbf75bf7b,0xbf62bf55,0xbef1bf0e,0xbef1bec4,0xbf62bf6d,0xbf75bf6d,0xbe95bec4,
0xbf22bf0e,0xbf46bf55,0xbf7fbf7b,0xbdc9be48,0xbf7bbf80,0x3e480000,0x3e480000,0x3f7b3f80,0xbf55bf6d,0x3f0e3ec4,0x3f0e3ec4,0x3f553f6d,
0xbf0ebf35,0x3f553f35,0x3f553f35,0x3f0e3f35,0xbe48bec4,0x3f7b3f6d,0x3f7b3f6d,0x3e483ec4,0x3e950000,0x3f753f80,0x3ef13f35,0xbf62bf35,
0x3f463f0e,0x3f223f55,0xbdc93e48,0xbf7fbf7b,0x3f7f3f6d,0x3dc93ec4,0xbf22bec4,0xbf46bf6d,0x3f623f7b,0xbef1be48,0xbf75bf55,0xbe95bf0e,
0x3f6d3f80,0xbec40000,0xbf6dbf80,0x3ec40000,0x3ec43f35,0xbf6dbf35,0xbec4bf35,0x3f6d3f35,0xbec40000,0xbf6dbf80,0x3ec40000,0x3f6d3f80,
0xbf6dbf35,0xbec4bf35,0x3f6d3f35,0x3ec43f35,0xbef10000,0xbf62bf80,0x3f753f35,0x3e953f35,0xbf7fbf55,0xbdc9bf0e,0x3f463f7b,0xbf22be48,
0xbf22bf6d,0x3f463ec4,0xbdc93ec4,0xbf7fbf6d,0x3e95be48,0x3f753f7b,0xbf62bf0e,0xbef1bf55,0xbf55bf80,0x3f0e0000,0xbf0e0000,0xbf55bf80,
0x3e48bec4,0x3f7b3f6d,0xbf7bbf6d,0x3e48bec4,0x3f7b3f35,0x3e483f35,0xbe48bf35,0x3f7b3f35,0x3f0e3f6d,0xbf55bec4,0x3f553ec4,0x3f0e3f6d,
0x3f220000,0x3f463f80,0xbdc9bf35,0x3f7f3f35,0x3f623f7b,0xbef13e48,0x3f753f0e,0x3e953f55,0xbe953ec4,0xbf75bf6d,0x3ef13f6d,0xbf62bec4,
0xbf7fbf55,0x3dc9bf0e,0xbf46be48,0xbf22bf7b,0x3f353f80,0xbf350000,0x3f353f80,0xbf350000,0xbf350000,0xbf35bf80,0xbf350000,0xbf35bf80,
0xbf35bf80,0x3f350000,0xbf35bf80,0x3f350000,0x3f350000,0x3f353f80,0x3f350000,0x3f353f80,0xbf460000,0xbf22bf80,0xbf7fbf35,0x3dc9bf35,
0xbef1bf7b,0x3f623e48,0x3e95bf0e,0x3f753f55,0x3f753ec4,0x3e953f6d,0x3f623f6d,0xbef13ec4,0x3dc93f55,0xbf7fbf0e,0xbf223e48,0xbf46bf7b,
0xbf0ebf80,0x3f550000,0x3f550000,0x3f0e3f80,0x3f7b3ec4,0x3e483f6d,0x3e483f6d,0xbf7bbec4,0xbe483f35,0xbf7bbf35,0xbf7bbf35,0x3e48bf35,
0xbf55bf6d,0x3f0ebec4,0x3f0ebec4,0x3f553f6d,0x3f620000,0x3ef13f80,0xbe953f35,0xbf75bf35,0xbdc93f55,0xbf7fbf0e,0xbf22bf7b,0x3f46be48,
0xbf46bf6d,0x3f22bec4,0x3f7f3ec4,0x3dc93f6d,0x3f753e48,0x3e953f7b,0xbef13f0e,0xbf62bf55,0x3ec43f80,0xbf6d0000,0xbec4bf80,0x3f6d0000,
0xbf6dbf35,0x3ec4bf35,0x3f6d3f35,0xbec43f35,0x3f6d0000,0x3ec43f80,0xbf6d0000,0xbec4bf80,0xbec43f35,0xbf6dbf35,0x3ec4bf35,0x3f6d3f35,
0xbf750000,0xbe95bf80,0x3f623f35,0xbef13f35,0x3f22bf0e,0x3f463f55,0xbf7fbe48,0xbdc9bf7b,0xbdc93f6d,0xbf7fbec4,0x3f46bec4,0x3f223f6d,
0xbef1bf7b,0x3f62be48,0xbe953f55,0xbf75bf0e,0xbe48bf80,0x3f7b0000,0xbf7b0000,0xbe48bf80,0x3f0e3f6d,0xbf553ec4,0x3f55bec4,0x3f0e3f6d,
0xbf55bf35,0x3f0ebf35,0xbf0e3f35,0xbf55bf35,0x3f7b3ec4,0xbe483f6d,0x3e48bf6d,0x3f7b3ec4,0x3f7f0000,0x3dc93f80,0x3f22bf35,0x3f463f35,
0xbf753e48,0xbe95bf7b,0xbef13f55,0xbf62bf0e,0x3f62bec4,0x3ef13f6d,0x3e95bf6d,0x3f753ec4,0xbf463f0e,0xbf22bf55,0xbdc93f7b,0xbf7fbe48,
0x3f80,0xbf800000,0x3f80,0xbf800000,0xbf80,0x3f800000,0xbf80,0x3f800000,0x3f80,0xbf800000,0x3f80,0xbf800000,
0xbf80,0x3f800000,0xbf80,0x3f800000,0xbf7f0000,0x3dc9bf80,0xbf22bf35,0x3f46bf35,0x3f753e48,0xbe953f7b,0x3ef13f55,0xbf623f0e,
0xbf62bec4,0x3ef1bf6d,0xbe95bf6d,0x3f75bec4,0x3f463f0e,0xbf223f55,0x3dc93f7b,0xbf7f3e48,0x3e48bf80,0x3f7b0000,0x3f7b0000,0xbe483f80,
0xbf0e3f6d,0xbf55bec4,0xbf55bec4,0x3f0ebf6d,0x3f55bf35,0x3f0e3f35,0x3f0e3f35,0xbf553f35,0xbf7b3ec4,0xbe48bf6d,0xbe48bf6d,0x3f7bbec4,
0x3f750000,0xbe953f80,0xbf623f35,0xbef1bf35,0xbf22bf0e,0x3f46bf55,0x3f7fbe48,0xbdc93f7b,0x3dc93f6d,0xbf7f3ec4,0xbf46bec4,0x3f22bf6d,
0x3ef1bf7b,0x3f623e48,0x3e953f55,0xbf753f0e,0xbec43f80,0xbf6d0000,0x3ec4bf80,0x3f6d0000,0x3f6dbf35,0x3ec43f35,0xbf6d3f35,0xbec4bf35,
0xbf6d0000,0x3ec4bf80,0x3f6d0000,0xbec43f80,0x3ec43f35,0xbf6d3f35,0xbec4bf35,0x3f6dbf35,0xbf620000,0x3ef1bf80,0x3e953f35,0xbf753f35,
0x3dc93f55,0xbf7f3f0e,0x3f22bf7b,0x3f463e48,0x3f46bf6d,0x3f223ec4,0xbf7f3ec4,0x3dc9bf6d,0xbf753e48,0x3e95bf7b,0x3ef13f0e,0xbf623f55,
0x3f0ebf80,0x3f550000,0xbf550000,0x3f0ebf80,0xbf7b3ec4,0x3e48bf6d,0xbe483f6d,0xbf7b3ec4,0x3e483f35,0xbf7b3f35,0x3f7bbf35,0x3e483f35,
0x3f55bf6d,0x3f0e3ec4,0xbf0ebec4,0x3f55bf6d,0x3f460000,0xbf223f80,0x3f7fbf35,0x3dc93f35,0x3ef1bf7b,0x3f62be48,0xbe95bf0e,0x3f75bf55,
0xbf753ec4,0x3e95bf6d,0xbf623f6d,0xbef1bec4,0xbdc93f55,0xbf7f3f0e,0x3f223e48,0xbf463f7b,0xbf353f80,0xbf350000,0xbf353f80,0xbf350000,
0x3f350000,0xbf353f80,0x3f350000,0xbf353f80,0x3f35bf80,0x3f350000,0x3f35bf80,0x3f350000,0xbf350000,0x3f35bf80,0xbf350000,0x3f35bf80,
0xbf220000,0x3f46bf80,0x3dc9bf35,0x3f7fbf35,0xbf623f7b,0xbef1be48,0xbf753f0e,0x3e95bf55,0x3e953ec4,0xbf753f6d,0xbef13f6d,0xbf623ec4,
0x3f7fbf55,0x3dc93f0e,0x3f46be48,0xbf223f7b,0x3f55bf80,0x3f0e0000,0x3f0e0000,0xbf553f80,0xbe48bec4,0x3f7bbf6d,0x3f7bbf6d,0x3e483ec4,
0xbf7b3f35,0x3e48bf35,0x3e48bf35,0x3f7bbf35,0xbf0e3f6d,0xbf553ec4,0xbf553ec4,0x3f0ebf6d,0x3ef10000,0xbf623f80,0xbf753f35,0x3e95bf35,
0x3f7fbf55,0xbdc93f0e,0xbf463f7b,0xbf223e48,0x3f22bf6d,0x3f46bec4,0x3dc93ec4,0xbf7f3f6d,0xbe95be48,0x3f75bf7b,0x3f62bf0e,0xbef13f55,
0xbf6d3f80,0xbec40000,0x3f6dbf80,0x3ec40000,0xbec43f35,0xbf6d3f35,0x3ec4bf35,0x3f6dbf35,0x3ec40000,0xbf6d3f80,0xbec40000,0x3f6dbf80,
0x3f6dbf35,0xbec43f35,0xbf6d3f35,0x3ec4bf35,0xbe950000,0x3f75bf80,0xbef13f35,0xbf623f35,0xbf463f0e,0x3f22bf55,0x3dc93e48,0xbf7f3f7b,
0xbf7f3f6d,0x3dc9bec4,0x3f22bec4,0xbf463f6d,0xbf623f7b,0xbef13e48,0x3f75bf55,0xbe953f0e,0x3f7bbf80,0x3e480000,0xbe480000,0x3f7bbf80,
0x3f55bf6d,0x3f0ebec4,0xbf0e3ec4,0x3f55bf6d,0x3f0ebf35,0x3f55bf35,0xbf553f35,0x3f0ebf35,0x3e48bec4,0x3f7bbf6d,0xbf7b3f6d,0x3e48bec4,
0x3dc90000,0xbf7f3f80,0x3f46bf35,0xbf223f35,0x3e95be48,0xbf753f7b,0x3f62bf55,0xbef13f0e,0x3ef1bec4,0xbf623f6d,0x3f75bf6d,0xbe953ec4,
0x3f22bf0e,0xbf463f55,0x3f7fbf7b,0xbdc93e48,0x3f803f80,0xbf803f80,0x3f803f80,0xbf803f80,0x3f803f80,0xbf803f80,0x3f803f80,0xbf803f80,
0x3f803f80,0xbf803f80,0x3f803f80,0xbf803f80,0x3f803f80,0xbf803f80,0x3f803f80,0xbf803f80,0xbf7fbf80,0x3dc90000,0xbf22bf35,0x3f463f35,
0xbf75bf7b,0x3e953e48,0xbef1bf0e,0x3f623f55,0xbf62bf6d,0x3ef13ec4,0xbe95bec4,0x3f753f6d,0xbf46bf55,0x3f223f0e,0xbdc9be48,0x3f7f3f7b,
0x3f7b3f80,0xbe480000,0xbe480000,0xbf7bbf80,0x3f553f6d,0xbf0ebec4,0xbf0ebec4,0xbf55bf6d,0x3f0e3f35,0xbf55bf35,0xbf55bf35,0xbf0ebf35,
0x3e483ec4,0xbf7bbf6d,0xbf7bbf6d,0xbe48bec4,0xbf75bf80,0x3e950000,0x3f623f35,0x3ef13f35,0xbf22bf55,0x3f463f0e,0x3f7f3f7b,0xbdc93e48,
0xbdc9bec4,0x3f7f3f6d,0x3f463f6d,0xbf22bec4,0x3ef13e48,0x3f623f7b,0x3e953f0e,0xbf75bf55,0x3f6d3f80,0xbec40000,0xbf6dbf80,0x3ec40000,
0x3ec43f35,0xbf6dbf35,0xbec4bf35,0x3f6d3f35,0xbec40000,0xbf6dbf80,0x3ec40000,0x3f6d3f80,0xbf6dbf35,0xbec4bf35,0x3f6d3f35,0x3ec43f35,
0xbf62bf80,0x3ef10000,0x3e953f35,0xbf75bf35,0xbdc9bf0e,0x3f7f3f55,0xbf22be48,0xbf46bf7b,0x3f463ec4,0x3f223f6d,0xbf7fbf6d,0x3dc9bec4,
0x3f753f7b,0xbe953e48,0xbef1bf55,0x3f623f0e,0x3f553f80,0xbf0e0000,0x3f0e0000,0x3f553f80,0xbe483ec4,0xbf7bbf6d,0x3f7b3f6d,0xbe483ec4,
0xbf7bbf35,0xbe48bf35,0x3e483f35,0xbf7bbf35,0xbf0ebf6d,0x3f553ec4,0xbf55bec4,0xbf0ebf6d,0xbf46bf80,0x3f220000,0xbf7fbf35,0xbdc9bf35,
0x3ef1be48,0x3f623f7b,0xbe95bf55,0x3f753f0e,0x3f753f6d,0xbe953ec4,0x3f623ec4,0x3ef13f6d,0xbdc93f0e,0xbf7fbf55,0x3f223f7b,0xbf46be48,
0x3f353f80,0xbf350000,0x3f353f80,0xbf350000,0xbf350000,0xbf35bf80,0xbf350000,0xbf35bf80,0xbf35bf80,0x3f350000,0xbf35bf80,0x3f350000,
0x3f350000,0x3f353f80,0x3f350000,0x3f353f80,0xbf22bf80,0x3f460000,0x3dc9bf35,0x3f7f3f35,0x3f623e48,0x3ef13f7b,0x3f753f55,0xbe953f0e,
0x3e953f6d,0xbf75bec4,0xbef13ec4,0xbf62bf6d,0xbf7fbf0e,0xbdc9bf55,0xbf46bf7b,0x3f22be48,0x3f0e3f80,0xbf550000,0xbf550000,0xbf0ebf80,
0xbf7bbec4,0xbe48bf6d,0xbe48bf6d,0x3f7b3ec4,0x3e48bf35,0x3f7b3f35,0x3f7b3f35,0xbe483f35,0x3f553f6d,0xbf0e3ec4,0xbf0e3ec4,0xbf55bf6d,
0xbef1bf80,0x3f620000,0x3f753f35,0xbe953f35,0x3f7f3f0e,0xbdc93f55,0xbf463e48,0xbf22bf7b,0xbf223ec4,0xbf46bf6d,0xbdc9bf6d,0x3f7f3ec4,
0xbe95bf7b,0x3f753e48,0x3f623f55,0xbef13f0e,0x3ec43f80,0xbf6d0000,0xbec4bf80,0x3f6d0000,0xbf6dbf35,0x3ec4bf35,0x3f6d3f35,0xbec43f35,
0x3f6d0000,0x3ec43f80,0xbf6d0000,0xbec4bf80,0xbec43f35,0xbf6dbf35,0x3ec4bf35,0x3f6d3f35,0xbe95bf80,0x3f750000,0xbef13f35,0xbf62bf35,
0x3f463f55,0xbf223f0e,0xbdc9bf7b,0x3f7f3e48,0xbf7fbec4,0x3dc9bf6d,0x3f223f6d,0xbf463ec4,0x3f62be48,0x3ef13f7b,0xbf75bf0e,0x3e95bf55,
0x3e483f80,0xbf7b0000,0x3f7b0000,0x3e483f80,0xbf0ebf6d,0x3f55bec4,0xbf553ec4,0xbf0ebf6d,0x3f553f35,0xbf0e3f35,0x3f0ebf35,0x3f553f35,
0xbf7bbec4,0x3e48bf6d,0xbe483f6d,0xbf7bbec4,0xbdc9bf80,0x3f7f0000,0xbf46bf35,0x3f22bf35,0x3e953f7b,0xbf753e48,0x3f623f0e,0xbef13f55,
0xbef1bf6d,0x3f62bec4,0xbf75bec4,0x3e95bf6d,0x3f223f55,0xbf463f0e,0x3f7f3e48,0xbdc93f7b,0x3f80,0xbf800000,0x3f80,0xbf800000,
0xbf80,0x3f800000,0xbf80,0x3f800000,0x3f80,0xbf800000,0x3f80,0xbf800000,0xbf80,0x3f800000,0xbf80,0x3f800000,
0x3dc9bf80,0x3f7f0000,0x3f46bf35,0x3f223f35,0xbe953f7b,0xbf75be48,0xbf623f0e,0xbef1bf55,0x3ef1bf6d,0x3f623ec4,0x3f75bec4,0x3e953f6d,
0xbf223f55,0xbf46bf0e,0xbf7f3e48,0xbdc9bf7b,0xbe483f80,0xbf7b0000,0xbf7b0000,0x3e48bf80,0x3f0ebf6d,0x3f553ec4,0x3f553ec4,0xbf0e3f6d,
0xbf553f35,0xbf0ebf35,0xbf0ebf35,0x3f55bf35,0x3f7bbec4,0x3e483f6d,0x3e483f6d,0xbf7b3ec4,0x3e95bf80,0x3f750000,0x3ef13f35,0xbf623f35,
0xbf463f55,0xbf22bf0e,0x3dc9bf7b,0x3f7fbe48,0x3f7fbec4,0x3dc93f6d,0xbf223f6d,0xbf46bec4,0xbf62be48,0x3ef1bf7b,0x3f75bf0e,0x3e953f55,
0xbec43f80,0xbf6d0000,0x3ec4bf80,0x3f6d0000,0x3f6dbf35,0x3ec43f35,0xbf6d3f35,0xbec4bf35,0xbf6d0000,0x3ec4bf80,0x3f6d0000,0xbec43f80,
0x3ec43f35,0xbf6d3f35,0xbec4bf35,0x3f6dbf35,0x3ef1bf80,0x3f620000,0xbf753f35,0xbe95bf35,0xbf7f3f0e,0xbdc9bf55,0x3f463e48,0xbf223f7b,
0x3f223ec4,0xbf463f6d,0x3dc9bf6d,0x3f7fbec4,0x3e95bf7b,0x3f75be48,0xbf623f55,0xbef1bf0e,0xbf0e3f80,0xbf550000,0x3f550000,0xbf0e3f80,
0x3f7bbec4,0xbe483f6d,0x3e48bf6d,0x3f7bbec4,0xbe48bf35,0x3f7bbf35,0xbf7b3f35,0xbe48bf35,0xbf553f6d,0xbf0ebec4,0x3f0e3ec4,0xbf553f6d,
0x3f22bf80,0x3f460000,0xbdc9bf35,0x3f7fbf35,0xbf623e48,0x3ef1bf7b,0xbf753f55,0xbe95bf0e,0xbe953f6d,0xbf753ec4,0x3ef13ec4,0xbf623f6d,
0x3f7fbf0e,0xbdc93f55,0x3f46bf7b,0x3f223e48,0xbf353f80,0xbf350000,0xbf353f80,0xbf350000,0x3f350000,0xbf353f80,0x3f350000,0xbf353f80,
0x3f35bf80,0x3f350000,0x3f35bf80,0x3f350000,0xbf350000,0x3f35bf80,0xbf350000,0x3f35bf80,0x3f46bf80,0x3f220000,0x3f7fbf35,0xbdc93f35,
0xbef1be48,0x3f62bf7b,0x3e95bf55,0x3f75bf0e,0xbf753f6d,0xbe95bec4,0xbf623ec4,0x3ef1bf6d,0x3dc93f0e,0xbf7f3f55,0xbf223f7b,0xbf463e48,
0xbf553f80,0xbf0e0000,0xbf0e0000,0x3f55bf80,0x3e483ec4,0xbf7b3f6d,0xbf7b3f6d,0xbe48bec4,0x3f7bbf35,0xbe483f35,0xbe483f35,0xbf7b3f35,
0x3f0ebf6d,0x3f55bec4,0x3f55bec4,0xbf0e3f6d,0x3f62bf80,0x3ef10000,0xbe953f35,0xbf753f35,0x3dc9bf0e,0x3f7fbf55,0x3f22be48,0xbf463f7b,
0xbf463ec4,0x3f22bf6d,0x3f7fbf6d,0x3dc93ec4,0xbf753f7b,0xbe95be48,0x3ef1bf55,0x3f62bf0e,0xbf6d3f80,0xbec40000,0x3f6dbf80,0x3ec40000,
0xbec43f35,0xbf6d3f35,0x3ec4bf35,0x3f6dbf35,0x3ec40000,0xbf6d3f80,0xbec40000,0x3f6dbf80,0x3f6dbf35,0xbec43f35,0xbf6d3f35,0x3ec4bf35,
0x3f75bf80,0x3e950000,0xbf623f35,0x3ef1bf35,0x3f22bf55,0x3f46bf0e,0xbf7f3f7b,0xbdc9be48,0x3dc9bec4,0x3f7fbf6d,0xbf463f6d,0xbf223ec4,
0xbef13e48,0x3f62bf7b,0xbe953f0e,0xbf753f55,0xbf7b3f80,0xbe480000,0x3e480000,0xbf7b3f80,0xbf553f6d,0xbf0e3ec4,0x3f0ebec4,0xbf553f6d,
0xbf0e3f35,0xbf553f35,0x3f55bf35,0xbf0e3f35,0xbe483ec4,0xbf7b3f6d,0x3f7bbf6d,0xbe483ec4,0x3f7fbf80,0x3dc90000,0x3f22bf35,0x3f46bf35,
0x3f75bf7b,0x3e95be48,0x3ef1bf0e,0x3f62bf55,0x3f62bf6d,0x3ef1bec4,0x3e95bec4,0x3f75bf6d,0x3f46bf55,0x3f22bf0e,0x3dc9be48,0x3f7fbf7b,
0x3f803f80,0xbf803f80,0x3f803f80,0xbf803f80,0x3f803f80,0xbf803f80,0x3f803f80,0xbf803f80,0x3f803f80,0xbf803f80,0x3f803f80,0xbf803f80,
0x3f803f80,0xbf803f80,0x3f803f80,0xbf803f80,0x3dc90000,0x3f7f3f80,0x3f463f35,0x3f223f35,0x3e953e48,0x3f753f7b,0x3f623f55,0x3ef13f0e,
0x3ef13ec4,0x3f623f6d,0x3f753f6d,0x3e953ec4,0x3f223f0e,0x3f463f55,0x3f7f3f7b,0x3dc93e48,0xbf7bbf80,0x3e480000,0x3e480000,0x3f7b3f80,
0xbf55bf6d,0x3f0e3ec4,0x3f0e3ec4,0x3f553f6d,0xbf0ebf35,0x3f553f35,0x3f553f35,0x3f0e3f35,0xbe48bec4,0x3f7b3f6d,0x3f7b3f6d,0x3e483ec4,
0xbe950000,0xbf75bf80,0xbef1bf35,0x3f623f35,0xbf46bf0e,0xbf22bf55,0x3dc9be48,0x3f7f3f7b,0xbf7fbf6d,0xbdc9bec4,0x3f223ec4,0x3f463f6d,
0xbf62bf7b,0x3ef13e48,0x3f753f55,0x3e953f0e,0x3f6d3f80,0xbec40000,0xbf6dbf80,0x3ec40000,0x3ec43f35,0xbf6dbf35,0xbec4bf35,0x3f6d3f35,
0xbec40000,0xbf6dbf80,0x3ec40000,0x3f6d3f80,0xbf6dbf35,0xbec4bf35,0x3f6d3f35,0x3ec43f35,0x3ef10000,0x3f623f80,0xbf75bf35,0xbe95bf35,
0x3f7f3f55,0x3dc93f0e,0xbf46bf7b,0x3f223e48,0x3f223f6d,0xbf46bec4,0x3dc9bec4,0x3f7f3f6d,0xbe953e48,0xbf75bf7b,0x3f623f0e,0x3ef13f55,
0xbf55bf80,0x3f0e0000,0xbf0e0000,0xbf55bf80,0x3e48bec4,0x3f7b3f6d,0xbf7bbf6d,0x3e48bec4,0x3f7b3f35,0x3e483f35,0xbe48bf35,0x3f7b3f35,
0x3f0e3f6d,0xbf55bec4,0x3f553ec4,0x3f0e3f6d,0xbf220000,0xbf46bf80,0x3dc93f35,0xbf7fbf35,0xbf62bf7b,0x3ef1be48,0xbf75bf0e,0xbe95bf55,
0x3e95bec4,0x3f753f6d,0xbef1bf6d,0x3f623ec4,0x3f7f3f55,0xbdc93f0e,0x3f463e48,0x3f223f7b,0x3f353f80,0xbf350000,0x3f353f80,0xbf350000,
0xbf350000,0xbf35bf80,0xbf350000,0xbf35bf80,0xbf35bf80,0x3f350000,0xbf35bf80,0x3f350000,0x3f350000,0x3f353f80,0x3f350000,0x3f353f80,
0x3f460000,0x3f223f80,0x3f7f3f35,0xbdc93f35,0x3ef13f7b,0xbf62be48,0xbe953f0e,0xbf75bf55,0xbf75bec4,0xbe95bf6d,0xbf62bf6d,0x3ef1bec4,
0xbdc9bf55,0x3f7f3f0e,0x3f22be48,0x3f463f7b,0xbf0ebf80,0x3f550000,0x3f550000,0x3f0e3f80,0x3f7b3ec4,0x3e483f6d,0x3e483f6d,0xbf7bbec4,
0xbe483f35,0xbf7bbf35,0xbf7bbf35,0x3e48bf35,0xbf55bf6d,0x3f0ebec4,0x3f0ebec4,0x3f553f6d,0xbf620000,0xbef1bf80,0x3e95bf35,0x3f753f35,
0x3dc9bf55,0x3f7f3f0e,0x3f223f7b,0xbf463e48,0x3f463f6d,0xbf223ec4,0xbf7fbec4,0xbdc9bf6d,0xbf75be48,0xbe95bf7b,0x3ef1bf0e,0x3f623f55,
0x3ec43f80,0xbf6d0000,0xbec4bf80,0x3f6d0000,0xbf6dbf35,0x3ec4bf35,0x3f6d3f35,0xbec43f35,0x3f6d0000,0x3ec43f80,0xbf6d0000,0xbec4bf80,
0xbec43f35,0xbf6dbf35,0x3ec4bf35,0x3f6d3f35,0x3f750000,0x3e953f80,0xbf62bf35,0x3ef1bf35,0xbf223f0e,0xbf46bf55,0x3f7f3e48,0x3dc93f7b,
0x3dc9bf6d,0x3f7f3ec4,0xbf463ec4,0xbf22bf6d,0x3ef13f7b,0xbf623e48,0x3e95bf55,0x3f753f0e,0xbe48bf80,0x3f7b0000,0xbf7b0000,0xbe48bf80,
0x3f0e3f6d,0xbf553ec4,0x3f55bec4,0x3f0e3f6d,0xbf55bf35,0x3f0ebf35,0xbf0e3f35,0xbf55bf35,0x3f7b3ec4,0xbe483f6d,0x3e48bf6d,0x3f7b3ec4,
0xbf7f0000,0xbdc9bf80,0xbf223f35,0xbf46bf35,0x3f75be48,0x3e953f7b,0x3ef1bf55,0x3f623f0e,0xbf623ec4,0xbef1bf6d,0xbe953f6d,0xbf75bec4,
0x3f46bf0e,0x3f223f55,0x3dc9bf7b,0x3f7f3e48,0x3f80,0xbf800000,0x3f80,0xbf800000,0xbf80,0x3f800000,0xbf80,0x3f800000,
0x3f80,0xbf800000,0x3f80,0xbf800000,0xbf80,0x3f800000,0xbf80,0x3f800000,0x3f7f0000,0xbdc93f80,0x3f223f35,0xbf463f35,
0xbf75be48,0x3e95bf7b,0xbef1bf55,0x3f62bf0e,0x3f623ec4,0xbef13f6d,0x3e953f6d,0xbf753ec4,0xbf46bf0e,0x3f22bf55,0xbdc9bf7b,0x3f7fbe48,
0x3e48bf80,0x3f7b0000,0x3f7b0000,0xbe483f80,0xbf0e3f6d,0xbf55bec4,0xbf55bec4,0x3f0ebf6d,0x3f55bf35,0x3f0e3f35,0x3f0e3f35,0xbf553f35,
0xbf7b3ec4,0xbe48bf6d,0xbe48bf6d,0x3f7bbec4,0xbf750000,0x3e95bf80,0x3f62bf35,0x3ef13f35,0x3f223f0e,0xbf463f55,0xbf7f3e48,0x3dc9bf7b,
0xbdc9bf6d,0x3f7fbec4,0x3f463ec4,0xbf223f6d,0xbef13f7b,0xbf62be48,0xbe95bf55,0x3f75bf0e,0xbec43f80,0xbf6d0000,0x3ec4bf80,0x3f6d0000,
0x3f6dbf35,0x3ec43f35,0xbf6d3f35,0xbec4bf35,0xbf6d0000,0x3ec4bf80,0x3f6d0000,0xbec43f80,0x3ec43f35,0xbf6d3f35,0xbec4bf35,0x3f6dbf35,
0x3f620000,0xbef13f80,0xbe95bf35,0x3f75bf35,0xbdc9bf55,0x3f7fbf0e,0xbf223f7b,0xbf46be48,0xbf463f6d,0xbf22bec4,0x3f7fbec4,0xbdc93f6d,
0x3f75be48,0xbe953f7b,0xbef1bf0e,0x3f62bf55,0x3f0ebf80,0x3f550000,0xbf550000,0x3f0ebf80,0xbf7b3ec4,0x3e48bf6d,0xbe483f6d,0xbf7b3ec4,
0x3e483f35,0xbf7b3f35,0x3f7bbf35,0x3e483f35,0x3f55bf6d,0x3f0e3ec4,0xbf0ebec4,0x3f55bf6d,0xbf460000,0x3f22bf80,0xbf7f3f35,0xbdc9bf35,
0xbef13f7b,0xbf623e48,0x3e953f0e,0xbf753f55,0x3f75bec4,0xbe953f6d,0x3f62bf6d,0x3ef13ec4,0x3dc9bf55,0x3f7fbf0e,0xbf22be48,0x3f46bf7b,
0xbf353f80,0xbf350000,0xbf353f80,0xbf350000,0x3f350000,0xbf353f80,0x3f350000,0xbf353f80,0x3f35bf80,0x3f350000,0x3f35bf80,0x3f350000,
0xbf350000,0x3f35bf80,0xbf350000,0x3f35bf80,0x3f220000,0xbf463f80,0xbdc93f35,0xbf7f3f35,0x3f62bf7b,0x3ef13e48,0x3f75bf0e,0xbe953f55,
0xbe95bec4,0x3f75bf6d,0x3ef1bf6d,0x3f62bec4,0xbf7f3f55,0xbdc9bf0e,0xbf463e48,0x3f22bf7b,0x3f55bf80,0x3f0e0000,0x3f0e0000,0xbf553f80,
0xbe48bec4,0x3f7bbf6d,0x3f7bbf6d,0x3e483ec4,0xbf7b3f35,0x3e48bf35,0x3e48bf35,0x3f7bbf35,0xbf0e3f6d,0xbf553ec4,0xbf553ec4,0x3f0ebf6d,
0xbef10000,0x3f62bf80,0x3f75bf35,0xbe953f35,0xbf7f3f55,0x3dc9bf0e,0x3f46bf7b,0x3f22be48,0xbf223f6d,0xbf463ec4,0xbdc9bec4,0x3f7fbf6d,
0x3e953e48,0xbf753f7b,0xbf623f0e,0x3ef1bf55,0xbf6d3f80,0xbec40000,0x3f6dbf80,0x3ec40000,0xbec43f35,0xbf6d3f35,0x3ec4bf35,0x3f6dbf35,
0x3ec40000,0xbf6d3f80,0xbec40000,0x3f6dbf80,0x3f6dbf35,0xbec43f35,0xbf6d3f35,0x3ec4bf35,0x3e950000,0xbf753f80,0x3ef1bf35,0x3f62bf35,
0x3f46bf0e,0xbf223f55,0xbdc9be48,0x3f7fbf7b,0x3f7fbf6d,0xbdc93ec4,0xbf223ec4,0x3f46bf6d,0x3f62bf7b,0x3ef1be48,0xbf753f55,0x3e95bf0e,
0x3f7bbf80,0x3e480000,0xbe480000,0x3f7bbf80,0x3f55bf6d,0x3f0ebec4,0xbf0e3ec4,0x3f55bf6d,0x3f0ebf35,0x3f55bf35,0xbf553f35,0x3f0ebf35,
0x3e48bec4,0x3f7bbf6d,0xbf7b3f6d,0x3e48bec4,0xbdc90000,0x3f7fbf80,0xbf463f35,0x3f22bf35,0xbe953e48,0x3f75bf7b,0xbf623f55,0x3ef1bf0e,
0xbef13ec4,0x3f62bf6d,0xbf753f6d,0x3e95bec4,0xbf223f0e,0x3f46bf55,0xbf7f3f7b,0x3dc9be48,0x40003f80,0x3fb53f80,0x3f80,0xbfb53f80,
0x40004000,0xbfb50000,0x0,0xbfb5c000,0x40004000,0xbfb5c000,0x0,0x3fb50000,0x40004000,0x3fb50000,0x0,0x3fb54000,
0x3fff3f80,0x3fa23f80,0xbe49bf80,0xbfc6bf80,0x3ff53ffb,0xbfe2bec8,0xbf15bec8,0xbf71bffb,0x3fe23fed,0xbf15bfed,0xbf71bf44,0x3ff53f44,
0x3fc63fd5,0x3fff3f8e,0xbfa2bf8e,0x3e493fd5,0x3ffb3f80,0x3f8e3f80,0xbec83f80,0xbfd53f80,0x3fd53fed,0xbffbbf44,0xbf8ebf44,0xbec8bfed,
0x3f8e3fb5,0x3ec8bfb5,0xbfd5bfb5,0x3ffb3fb5,0x3ec83f44,0x3fd53fed,0xbffbbfed,0xbf8e3f44,0x3ff53f80,0x3f713f80,0xbf15bf80,0xbfe2bf80,
0x3fa23fd5,0xbfffbf8e,0xbfc6bf8e,0x3e49bfd5,0x3e493f44,0x3fa2bf44,0xbfffbfed,0x3fc63fed,0xbf71bec8,0x3f153ffb,0xbfe2bffb,0xbff5bec8,
0x3fed3f80,0x3f443f80,0xbf443f80,0xbfed3f80,0x3f443fb5,0xbfedbfb5,0xbfedbfb5,0x3f44bfb5,0xbf440000,0x3fed0000,0xbfedc000,0x3f444000,
0xbfedbfb5,0xbf443fb5,0xbf44bfb5,0xbfedbfb5,0x3fe23f80,0x3f153f80,0xbf71bf80,0xbff5bf80,0x3e493f8e,0xbfc6bfd5,0xbfffbfd5,0x3fa2bf8e,
0xbfc6bf44,0x3fff3f44,0xbfa2bfed,0xbe493fed,0xbff5bffb,0xbfe23ec8,0x3f15bec8,0xbf71bffb,0x3fd53f80,0x3ec83f80,0xbf8e3f80,0xbffb3f80,
0xbec83f44,0xbf8ebfed,0xbffbbfed,0x3fd5bf44,0xbffbbfb5,0x3fd53fb5,0xbec8bfb5,0xbf8e3fb5,0xbf8ebfed,0xbffbbf44,0x3fd53f44,0x3ec8bfed,
0x3fc63f80,0x3e493f80,0xbfa2bf80,0xbfffbf80,0xbf713ec8,0xbf15bffb,0xbfe2bffb,0x3ff5bec8,0xbff5bfed,0x3f713fed,0x3f15bf44,0xbfe23f44,
0x3e49bf8e,0xbfa2bfd5,0x3fff3fd5,0x3fc6bf8e,0x3f80,0xbfb53f80,0xc0003f80,0xbfb53f80,0xc000,0x3fb50000,0x40000000,0xbfb54000,
0x4000,0x3fb5c000,0xc0000000,0x3fb50000,0xc000,0xbfb50000,0x40000000,0x3fb5c000,0xbe493f80,0xbfc63f80,0xbfffbf80,0xbfa2bf80,
0x3f15bffb,0x3f713ec8,0x3ff53ec8,0xbfe23ffb,0xbf713fed,0x3ff5bfed,0xbfe2bf44,0x3f153f44,0x3fa2bfd5,0xbe49bf8e,0x3fc63f8e,0x3fffbfd5,
0xbec83f80,0xbfd53f80,0xbffb3f80,0xbf8e3f80,0x3f8ebfed,0x3ec83f44,0x3fd53f44,0xbffb3fed,0xbfd53fb5,0x3ffbbfb5,0xbf8ebfb5,0xbec83fb5,
0x3ffbbf44,0x3f8ebfed,0x3ec83fed,0x3fd5bf44,0xbf153f80,0xbfe23f80,0xbff5bf80,0xbf71bf80,0x3fc6bfd5,0xbe493f8e,0x3fa23f8e,0xbfff3fd5,
0xbfff3f44,0x3fc6bf44,0xbe49bfed,0xbfa23fed,0x3fe23ec8,0x3ff5bffb,0xbf713ffb,0x3f153ec8,0xbf443f80,0xbfed3f80,0xbfed3f80,0xbf443f80,
0x3fedbfb5,0xbf443fb5,0x3f443fb5,0xbfed3fb5,0xbfed0000,0x3f440000,0x3f44c000,0xbfed4000,0x3f443fb5,0x3fedbfb5,0xbfed3fb5,0xbf443fb5,
0xbf713f80,0xbff53f80,0xbfe2bf80,0xbf15bf80,0x3fffbf8e,0xbfa23fd5,0x3e493fd5,0xbfc63f8e,0xbfa2bf44,0xbe493f44,0x3fc6bfed,0xbfff3fed,
0xbf153ffb,0x3f71bec8,0xbff53ec8,0xbfe23ffb,0xbf8e3f80,0xbffb3f80,0xbfd53f80,0xbec83f80,0x3ffbbf44,0xbfd53fed,0xbec83fed,0xbf8e3f44,
0xbec8bfb5,0xbf8e3fb5,0x3ffbbfb5,0xbfd53fb5,0xbfd53fed,0xbec83f44,0xbf8ebf44,0xbffb3fed,0xbfa23f80,0xbfff3f80,0xbfc6bf80,0xbe49bf80,
0x3fe2bec8,0xbff53ffb,0xbf713ffb,0xbf153ec8,0x3f15bfed,0xbfe23fed,0x3ff5bf44,0xbf713f44,0xbfff3f8e,0xbfc63fd5,0x3e49bfd5,0xbfa23f8e,
0xc0003f80,0xbfb53f80,0x3f80,0x3fb53f80,0xc0004000,0x3fb50000,0x0,0x3fb5c000,0xc0004000,0x3fb5c000,0x0,0xbfb50000,
0xc0004000,0xbfb50000,0x0,0xbfb54000,0xbfff3f80,0xbfa23f80,0x3e49bf80,0x3fc6bf80,0xbff53ffb,0x3fe2bec8,0x3f15bec8,0x3f71bffb,
0xbfe23fed,0x3f15bfed,0x3f71bf44,0xbff53f44,0xbfc63fd5,0xbfff3f8e,0x3fa2bf8e,0xbe493fd5,0xbffb3f80,0xbf8e3f80,0x3ec83f80,0x3fd53f80,
0xbfd53fed,0x3ffbbf44,0x3f8ebf44,0x3ec8bfed,0xbf8e3fb5,0xbec8bfb5,0x3fd5bfb5,0xbffb3fb5,0xbec83f44,0xbfd53fed,0x3ffbbfed,0x3f8e3f44,
0xbff53f80,0xbf713f80,0x3f15bf80,0x3fe2bf80,0xbfa23fd5,0x3fffbf8e,0x3fc6bf8e,0xbe49bfd5,0xbe493f44,0xbfa2bf44,0x3fffbfed,0xbfc63fed,
0x3f71bec8,0xbf153ffb,0x3fe2bffb,0x3ff5bec8,0xbfed3f80,0xbf443f80,0x3f443f80,0x3fed3f80,0xbf443fb5,0x3fedbfb5,0x3fedbfb5,0xbf44bfb5,
0x3f440000,0xbfed0000,0x3fedc000,0xbf444000,0x3fedbfb5,0x3f443fb5,0x3f44bfb5,0x3fedbfb5,0xbfe23f80,0xbf153f80,0x3f71bf80,0x3ff5bf80,
0xbe493f8e,0x3fc6bfd5,0x3fffbfd5,0xbfa2bf8e,0x3fc6bf44,0xbfff3f44,0x3fa2bfed,0x3e493fed,0x3ff5bffb,0x3fe23ec8,0xbf15bec8,0x3f71bffb,
0xbfd53f80,0xbec83f80,0x3f8e3f80,0x3ffb3f80,0x3ec83f44,0x3f8ebfed,0x3ffbbfed,0xbfd5bf44,0x3ffbbfb5,0xbfd53fb5,0x3ec8bfb5,0x3f8e3fb5,
0x3f8ebfed,0x3ffbbf44,0xbfd53f44,0xbec8bfed,0xbfc63f80,0xbe493f80,0x3fa2bf80,0x3fffbf80,0x3f713ec8,0x3f15bffb,0x3fe2bffb,0xbff5bec8,
0x3ff5bfed,0xbf713fed,0xbf15bf44,0x3fe23f44,0xbe49bf8e,0x3fa2bfd5,0xbfff3fd5,0xbfc6bf8e,0x3f80,0x3fb53f80,0x40003f80,0x3fb53f80,
0xc000,0xbfb50000,0xc0000000,0x3fb54000,0x4000,0xbfb5c000,0x40000000,0xbfb50000,0xc000,0x3fb50000,0xc0000000,0xbfb5c000,
0x3e493f80,0x3fc63f80,0x3fffbf80,0x3fa2bf80,0xbf15bffb,0xbf713ec8,0xbff53ec8,0x3fe23ffb,0x3f713fed,0xbff5bfed,0x3fe2bf44,0xbf153f44,
0xbfa2bfd5,0x3e49bf8e,0xbfc63f8e,0xbfffbfd5,0x3ec83f80,0x3fd53f80,0x3ffb3f80,0x3f8e3f80,0xbf8ebfed,0xbec83f44,0xbfd53f44,0x3ffb3fed,
0x3fd53fb5,0xbffbbfb5,0x3f8ebfb5,0x3ec83fb5,0xbffbbf44,0xbf8ebfed,0xbec83fed,0xbfd5bf44,0x3f153f80,0x3fe23f80,0x3ff5bf80,0x3f71bf80,
0xbfc6bfd5,0x3e493f8e,0xbfa23f8e,0x3fff3fd5,0x3fff3f44,0xbfc6bf44,0x3e49bfed,0x3fa23fed,0xbfe23ec8,0xbff5bffb,0x3f713ffb,0xbf153ec8,
0x3f443f80,0x3fed3f80,0x3fed3f80,0x3f443f80,0xbfedbfb5,0x3f443fb5,0xbf443fb5,0x3fed3fb5,0x3fed0000,0xbf440000,0xbf44c000,0x3fed4000,
0xbf443fb5,0xbfedbfb5,0x3fed3fb5,0x3f443fb5,0x3f713f80,0x3ff53f80,0x3fe2bf80,0x3f15bf80,0xbfffbf8e,0x3fa23fd5,0xbe493fd5,0x3fc63f8e,
0x3fa2bf44,0x3e493f44,0xbfc6bfed,0x3fff3fed,0x3f153ffb,0xbf71bec8,0x3ff53ec8,0x3fe23ffb,0x3f8e3f80,0x3ffb3f80,0x3fd53f80,0x3ec83f80,
0xbffbbf44,0x3fd53fed,0x3ec83fed,0x3f8e3f44,0x3ec8bfb5,0x3f8e3fb5,0xbffbbfb5,0x3fd53fb5,0x3fd53fed,0x3ec83f44,0x3f8ebf44,0x3ffb3fed,
0x3fa23f80,0x3fff3f80,0x3fc6bf80,0x3e49bf80,0xbfe2bec8,0x3ff53ffb,0x3f713ffb,0x3f153ec8,0xbf15bfed,0x3fe23fed,0xbff5bf44,0x3f713f44,
0x3fff3f8e,0x3fc63fd5,0xbe49bfd5,0x3fa23f8e,0x40004000,0x3fb54000,0x0,0xbfb50000,0x40004000,0xbfb50000,0x0,0xbfb5c000,
0x40004000,0xbfb5c000,0x0,0x3fb50000,0x40004000,0x3fb50000,0x0,0x3fb54000,0x3fa23fb5,0xbe493fb5,0xbfc6bfb5,0xbfffbfb5,
0x3f713f8e,0xbff5bfd5,0xbfe2bfd5,0x3f15bf8e,0x3f153f44,0x3f71bf44,0xbff5bfed,0x3fe23fed,0x3e493ec8,0x3fc63ffb,0xbfffbffb,0xbfa23ec8,
0xbec80000,0xbfd50000,0xbffbc000,0xbf8ec000,0xbf8ebf44,0xbec8bfed,0xbfd5bfed,0x3ffb3f44,0xbfd5bfb5,0x3ffb3fb5,0xbf8ebfb5,0xbec83fb5,
0xbffbbfed,0xbf8e3f44,0xbec8bf44,0xbfd5bfed,0xbfe2bfb5,0xbff5bfb5,0xbf71bfb5,0x3f15bfb5,0xbfffbffb,0x3fc6bec8,0x3e49bec8,0x3fa23ffb,
0xbfc6bfed,0x3e493fed,0x3fa23f44,0xbfffbf44,0xbf15bf8e,0xbfe2bfd5,0x3ff53fd5,0x3f71bf8e,0xbfedc000,0xbf44c000,0x3f440000,0x3fed0000,
0xbf44bfb5,0x3fed3fb5,0x3fed3fb5,0xbf443fb5,0x3f440000,0xbfed0000,0x3fed4000,0xbf44c000,0x3fed3fb5,0x3f44bfb5,0x3f443fb5,0x3fed3fb5,
0xbf15bfb5,0x3f71bfb5,0x3ff53fb5,0x3fe23fb5,0x3fa23ec8,0x3e493ffb,0x3fc63ffb,0xbfffbec8,0x3fff3fed,0xbfa2bfed,0xbe493f44,0x3fc6bf44,
0x3f713fd5,0x3ff53f8e,0xbfe2bf8e,0xbf153fd5,0x3f8e0000,0x3ffb0000,0x3fd54000,0x3ec84000,0x3ffb3fed,0xbfd53f44,0xbec83f44,0xbf8ebfed,
0x3ec83fb5,0x3f8ebfb5,0xbffbbfb5,0x3fd53fb5,0xbfd5bf44,0xbec83fed,0xbf8ebfed,0xbffbbf44,0x3fff3fb5,0x3fc63fb5,0x3e493fb5,0xbfa23fb5,
0x3f153fd5,0xbfe2bf8e,0xbff5bf8e,0x3f71bfd5,0xbfe2bf44,0x3ff53f44,0xbf71bfed,0xbf153fed,0xbfa2bffb,0xbfffbec8,0x3fc63ec8,0x3e49bffb,
0x4000,0xbfb54000,0xc0000000,0xbfb50000,0xc000,0x3fb50000,0x40000000,0xbfb54000,0x4000,0x3fb5c000,0xc0000000,0x3fb50000,
0xc000,0xbfb50000,0x40000000,0x3fb5c000,0xbfc63fb5,0xbfff3fb5,0xbfa2bfb5,0x3e49bfb5,0x3fe2bf8e,0xbf153fd5,0x3f713fd5,0xbff53f8e,
0xbff53f44,0x3fe2bf44,0xbf15bfed,0xbf713fed,0x3fffbec8,0x3fa2bffb,0x3e493ffb,0x3fc6bec8,0xbffb0000,0xbf8e0000,0x3ec8c000,0x3fd5c000,
0x3fd53f44,0xbffb3fed,0xbf8e3fed,0xbec8bf44,0xbf8ebfb5,0xbec83fb5,0x3fd5bfb5,0xbffb3fb5,0x3ec83fed,0x3fd5bf44,0xbffb3f44,0xbf8e3fed,
0xbf71bfb5,0x3f15bfb5,0x3fe2bfb5,0x3ff5bfb5,0xbe493ffb,0xbfa23ec8,0xbfff3ec8,0x3fc6bffb,0x3fa2bfed,0xbfff3fed,0x3fc63f44,0xbe49bf44,
0xbff53f8e,0xbf713fd5,0xbf15bfd5,0xbfe23f8e,0x3f44c000,0x3fedc000,0x3fed0000,0x3f440000,0xbfed3fb5,0x3f44bfb5,0xbf44bfb5,0x3fedbfb5,
0x3fed0000,0xbf440000,0xbf444000,0x3fedc000,0xbf44bfb5,0xbfed3fb5,0x3fedbfb5,0x3f44bfb5,0x3ff5bfb5,0x3fe2bfb5,0x3f153fb5,0xbf713fb5,
0xbfc6bec8,0x3fffbffb,0x3fa2bffb,0x3e493ec8,0xbe493fed,0x3fc6bfed,0xbfff3f44,0x3fa2bf44,0x3fe2bfd5,0x3f15bf8e,0x3f713f8e,0x3ff5bfd5,
0x3fd50000,0x3ec80000,0xbf8e4000,0xbffb4000,0x3ec8bfed,0x3f8ebf44,0x3ffbbf44,0xbfd53fed,0xbffb3fb5,0x3fd5bfb5,0xbec8bfb5,0xbf8e3fb5,
0x3f8e3f44,0x3ffbbfed,0xbfd53fed,0xbec83f44,0x3e493fb5,0xbfa23fb5,0xbfff3fb5,0xbfc63fb5,0x3ff5bfd5,0xbf713f8e,0x3f153f8e,0xbfe23fd5,
0xbf71bf44,0xbf153f44,0x3fe2bfed,0xbff53fed,0xbfc63ffb,0xbe493ec8,0xbfa2bec8,0xbfff3ffb,0xc0004000,0xbfb54000,0x0,0x3fb50000,
0xc0004000,0x3fb50000,0x0,0x3fb5c000,0xc0004000,0x3fb5c000,0x0,0xbfb50000,0xc0004000,0xbfb50000,0x0,0xbfb54000,
0xbfa23fb5,0x3e493fb5,0x3fc6bfb5,0x3fffbfb5,0xbf713f8e,0x3ff5bfd5,0x3fe2bfd5,0xbf15bf8e,0xbf153f44,0xbf71bf44,0x3ff5bfed,0xbfe23fed,
0xbe493ec8,0xbfc63ffb,0x3fffbffb,0x3fa23ec8,0x3ec80000,0x3fd50000,0x3ffbc000,0x3f8ec000,0x3f8ebf44,0x3ec8bfed,0x3fd5bfed,0xbffb3f44,
0x3fd5bfb5,0xbffb3fb5,0x3f8ebfb5,0x3ec83fb5,0x3ffbbfed,0x3f8e3f44,0x3ec8bf44,0x3fd5bfed,0x3fe2bfb5,0x3ff5bfb5,0x3f71bfb5,0xbf15bfb5,
0x3fffbffb,0xbfc6bec8,0xbe49bec8,0xbfa23ffb,0x3fc6bfed,0xbe493fed,0xbfa23f44,0x3fffbf44,0x3f15bf8e,0x3fe2bfd5,0xbff53fd5,0xbf71bf8e,
0x3fedc000,0x3f44c000,0xbf440000,0xbfed0000,0x3f44bfb5,0xbfed3fb5,0xbfed3fb5,0x3f443fb5,0xbf440000,0x3fed0000,0xbfed4000,0x3f44c000,
0xbfed3fb5,0xbf44bfb5,0xbf443fb5,0xbfed3fb5,0x3f15bfb5,0xbf71bfb5,0xbff53fb5,0xbfe23fb5,0xbfa23ec8,0xbe493ffb,0xbfc63ffb,0x3fffbec8,
0xbfff3fed,0x3fa2bfed,0x3e493f44,0xbfc6bf44,0xbf713fd5,0xbff53f8e,0x3fe2bf8e,0x3f153fd5,0xbf8e0000,0xbffb0000,0xbfd54000,0xbec84000,
0xbffb3fed,0x3fd53f44,0x3ec83f44,0x3f8ebfed,0xbec83fb5,0xbf8ebfb5,0x3ffbbfb5,0xbfd53fb5,0x3fd5bf44,0x3ec83fed,0x3f8ebfed,0x3ffbbf44,
0xbfff3fb5,0xbfc63fb5,0xbe493fb5,0x3fa23fb5,0xbf153fd5,0x3fe2bf8e,0x3ff5bf8e,0xbf71bfd5,0x3fe2bf44,0xbff53f44,0x3f71bfed,0x3f153fed,
0x3fa2bffb,0x3fffbec8,0xbfc63ec8,0xbe49bffb,0x4000,0x3fb54000,0x40000000,0x3fb50000,0xc000,0xbfb50000,0xc0000000,0x3fb54000,
0x4000,0xbfb5c000,0x40000000,0xbfb50000,0xc000,0x3fb50000,0xc0000000,0xbfb5c000,0x3fc63fb5,0x3fff3fb5,0x3fa2bfb5,0xbe49bfb5,
0xbfe2bf8e,0x3f153fd5,0xbf713fd5,0x3ff53f8e,0x3ff53f44,0xbfe2bf44,0x3f15bfed,0x3f713fed,0xbfffbec8,0xbfa2bffb,0xbe493ffb,0xbfc6bec8,
0x3ffb0000,0x3f8e0000,0xbec8c000,0xbfd5c000,0xbfd53f44,0x3ffb3fed,0x3f8e3fed,0x3ec8bf44,0x3f8ebfb5,0x3ec83fb5,0xbfd5bfb5,0x3ffb3fb5,
0xbec83fed,0xbfd5bf44,0x3ffb3f44,0x3f8e3fed,0x3f71bfb5,0xbf15bfb5,0xbfe2bfb5,0xbff5bfb5,0x3e493ffb,0x3fa23ec8,0x3fff3ec8,0xbfc6bffb,
0xbfa2bfed,0x3fff3fed,0xbfc63f44,0x3e49bf44,0x3ff53f8e,0x3f713fd5,0x3f15bfd5,0x3fe23f8e,0xbf44c000,0xbfedc000,0xbfed0000,0xbf440000,
0x3fed3fb5,0xbf44bfb5,0x3f44bfb5,0xbfedbfb5,0xbfed0000,0x3f440000,0x3f444000,0xbfedc000,0x3f44bfb5,0x3fed3fb5,0xbfedbfb5,0xbf44bfb5,
0xbff5bfb5,0xbfe2bfb5,0xbf153fb5,0x3f713fb5,0x3fc6bec8,0xbfffbffb,0xbfa2bffb,0xbe493ec8,0x3e493fed,0xbfc6bfed,0x3fff3f44,0xbfa2bf44,
0xbfe2bfd5,0xbf15bf8e,0xbf713f8e,0xbff5bfd5,0xbfd50000,0xbec80000,0x3f8e4000,0x3ffb4000,0xbec8bfed,0xbf8ebf44,0xbffbbf44,0x3fd53fed,
0x3ffb3fb5,0xbfd5bfb5,0x3ec8bfb5,0x3f8e3fb5,0xbf8e3f44,0xbffbbfed,0x3fd53fed,0x3ec83f44,0xbe493fb5,0x3fa23fb5,0x3fff3fb5,0x3fc63fb5,
0xbff5bfd5,0x3f713f8e,0xbf153f8e,0x3fe23fd5,0x3f71bf44,0x3f153f44,0xbfe2bfed,0x3ff53fed,0x3fc63ffb,0x3e493ec8,0x3fa2bec8,0x3fff3ffb,
0x40004000,0x3fb54000,0x0,0xbfb50000,0x40004000,0xbfb50000,0x0,0xbfb5c000,0x40004000,0xbfb5c000,0x0,0x3fb50000,
0x40004000,0x3fb50000,0x0,0x3fb54000,0xbe490000,0xbfc60000,0xbfffc000,0xbfa2c000,0xbf15bec8,0xbf71bffb,0xbff5bffb,0x3fe23ec8,
0xbf71bf44,0x3ff53f44,0xbfe2bfed,0x3f153fed,0xbfa2bf8e,0x3e493fd5,0xbfc6bfd5,0xbfffbf8e,0xbffbc000,0xbf8ec000,0x3ec80000,0x3fd50000,
0xbfd5bfed,0x3ffb3f44,0x3f8e3f44,0x3ec83fed,0xbf8ebfb5,0xbec83fb5,0x3fd53fb5,0xbffbbfb5,0xbec8bf44,0xbfd5bfed,0x3ffb3fed,0x3f8ebf44,
0x3f150000,0x3fe20000,0x3ff54000,0x3f714000,0x3fc63f8e,0xbe493fd5,0x3fa23fd5,0xbfffbf8e,0x3fff3fed,0xbfc6bfed,0x3e493f44,0x3fa2bf44,
0x3fe23ffb,0x3ff53ec8,0xbf71bec8,0x3f153ffb,0x3fed4000,0x3f444000,0xbf440000,0xbfed0000,0x3f443fb5,0xbfedbfb5,0xbfedbfb5,0x3f44bfb5,
0xbf440000,0x3fed0000,0xbfedc000,0x3f444000,0xbfedbfb5,0xbf443fb5,0xbf44bfb5,0xbfedbfb5,0xbf710000,0xbff50000,0xbfe2c000,0xbf15c000,
0xbfffbfd5,0x3fa2bf8e,0xbe49bf8e,0x3fc63fd5,0xbfa2bfed,0xbe493fed,0x3fc63f44,0xbfffbf44,0x3f15bec8,0xbf71bffb,0x3ff53ffb,0x3fe2bec8,
0xbfd5c000,0xbec8c000,0x3f8e0000,0x3ffb0000,0x3ec8bf44,0x3f8e3fed,0x3ffb3fed,0xbfd53f44,0x3ffb3fb5,0xbfd5bfb5,0x3ec83fb5,0x3f8ebfb5,
0x3f8e3fed,0x3ffb3f44,0xbfd5bf44,0xbec83fed,0x3fa20000,0x3fff0000,0x3fc64000,0x3e494000,0x3fe23ffb,0xbff53ec8,0xbf713ec8,0xbf15bffb,
0xbf153f44,0x3fe2bf44,0xbff5bfed,0x3f713fed,0xbfffbfd5,0xbfc63f8e,0x3e49bf8e,0xbfa2bfd5,0x4000,0xbfb54000,0xc0000000,0xbfb50000,
0xc000,0x3fb50000,0x40000000,0xbfb54000,0x4000,0x3fb5c000,0xc0000000,0x3fb50000,0xc000,0xbfb50000,0x40000000,0x3fb5c000,
0xbfff0000,0xbfa20000,0x3e49c000,0x3fc6c000,0x3ff53ec8,0xbfe23ffb,0xbf153ffb,0xbf71bec8,0xbfe2bf44,0x3f153f44,0x3f71bfed,0xbff53fed,
0x3fc63f8e,0x3fffbfd5,0xbfa23fd5,0x3e493f8e,0x3ec8c000,0x3fd5c000,0x3ffb0000,0x3f8e0000,0xbf8e3fed,0xbec8bf44,0xbfd5bf44,0x3ffbbfed,
0x3fd5bfb5,0xbffb3fb5,0x3f8e3fb5,0x3ec8bfb5,0xbffb3f44,0xbf8e3fed,0xbec8bfed,0xbfd53f44,0x3ff50000,0x3f710000,0xbf154000,0xbfe24000,
0xbfa2bf8e,0x3fffbfd5,0x3fc6bfd5,0xbe493f8e,0x3e493fed,0x3fa2bfed,0xbfff3f44,0x3fc6bf44,0x3f71bffb,0xbf15bec8,0x3fe23ec8,0x3ff5bffb,
0xbf444000,0xbfed4000,0xbfed0000,0xbf440000,0x3fedbfb5,0xbf443fb5,0x3f443fb5,0xbfed3fb5,0xbfed0000,0x3f440000,0x3f44c000,0xbfed4000,
0x3f443fb5,0x3fedbfb5,0xbfed3fb5,0xbf443fb5,0xbfe20000,0xbf150000,0x3f71c000,0x3ff5c000,0x3e493fd5,0xbfc63f8e,0xbfff3f8e,0x3fa2bfd5,
0x3fc6bfed,0xbfff3fed,0x3fa23f44,0x3e49bf44,0xbff53ec8,0xbfe23ffb,0x3f15bffb,0xbf713ec8,0x3f8ec000,0x3ffbc000,0x3fd50000,0x3ec80000,
0xbffb3f44,0x3fd5bfed,0x3ec8bfed,0x3f8ebf44,0x3ec83fb5,0x3f8ebfb5,0xbffb3fb5,0x3fd5bfb5,0x3fd5bfed,0x3ec8bf44,0x3f8e3f44,0x3ffbbfed,
0x3fc60000,0x3e490000,0xbfa24000,0xbfff4000,0x3f71bffb,0x3f15bec8,0x3fe2bec8,0xbff53ffb,0xbff53f44,0x3f71bf44,0x3f15bfed,0xbfe23fed,
0xbe493fd5,0x3fa2bf8e,0xbfff3f8e,0xbfc63fd5,0xc0004000,0xbfb54000,0x0,0x3fb50000,0xc0004000,0x3fb50000,0x0,0x3fb5c000,
0xc0004000,0x3fb5c000,0x0,0xbfb50000,0xc0004000,0xbfb50000,0x0,0xbfb54000,0x3e490000,0x3fc60000,0x3fffc000,0x3fa2c000,
0x3f15bec8,0x3f71bffb,0x3ff5bffb,0xbfe23ec8,0x3f71bf44,0xbff53f44,0x3fe2bfed,0xbf153fed,0x3fa2bf8e,0xbe493fd5,0x3fc6bfd5,0x3fffbf8e,
0x3ffbc000,0x3f8ec000,0xbec80000,0xbfd50000,0x3fd5bfed,0xbffb3f44,0xbf8e3f44,0xbec83fed,0x3f8ebfb5,0x3ec83fb5,0xbfd53fb5,0x3ffbbfb5,
0x3ec8bf44,0x3fd5bfed,0xbffb3fed,0xbf8ebf44,0xbf150000,0xbfe20000,0xbff54000,0xbf714000,0xbfc63f8e,0x3e493fd5,0xbfa23fd5,0x3fffbf8e,
0xbfff3fed,0x3fc6bfed,0xbe493f44,0xbfa2bf44,0xbfe23ffb,0xbff53ec8,0x3f71bec8,0xbf153ffb,0xbfed4000,0xbf444000,0x3f440000,0x3fed0000,
0xbf443fb5,0x3fedbfb5,0x3fedbfb5,0xbf44bfb5,0x3f440000,0xbfed0000,0x3fedc000,0xbf444000,0x3fedbfb5,0x3f443fb5,0x3f44bfb5,0x3fedbfb5,
0x3f710000,0x3ff50000,0x3fe2c000,0x3f15c000,0x3fffbfd5,0xbfa2bf8e,0x3e49bf8e,0xbfc63fd5,0x3fa2bfed,0x3e493fed,0xbfc63f44,0x3fffbf44,
0xbf15bec8,0x3f71bffb,0xbff53ffb,0xbfe2bec8,0x3fd5c000,0x3ec8c000,0xbf8e0000,0xbffb0000,0xbec8bf44,0xbf8e3fed,0xbffb3fed,0x3fd53f44,
0xbffb3fb5,0x3fd5bfb5,0xbec83fb5,0xbf8ebfb5,0xbf8e3fed,0xbffb3f44,0x3fd5bf44,0x3ec83fed,0xbfa20000,0xbfff0000,0xbfc64000,0xbe494000,
0xbfe23ffb,0x3ff53ec8,0x3f713ec8,0x3f15bffb,0x3f153f44,0xbfe2bf44,0x3ff5bfed,0xbf713fed,0x3fffbfd5,0x3fc63f8e,0xbe49bf8e,0x3fa2bfd5,
0x4000,0x3fb54000,0x40000000,0x3fb50000,0xc000,0xbfb50000,0xc0000000,0x3fb54000,0x4000,0xbfb5c000,0x40000000,0xbfb50000,
0xc000,0x3fb50000,0xc0000000,0xbfb5c000,0x3fff0000,0x3fa20000,0xbe49c000,0xbfc6c000,0xbff53ec8,0x3fe23ffb,0x3f153ffb,0x3f71bec8,
0x3fe2bf44,0xbf153f44,0xbf71bfed,0x3ff53fed,0xbfc63f8e,0xbfffbfd5,0x3fa23fd5,0xbe493f8e,0xbec8c000,0xbfd5c000,0xbffb0000,0xbf8e0000,
0x3f8e3fed,0x3ec8bf44,0x3fd5bf44,0xbffbbfed,0xbfd5bfb5,0x3ffb3fb5,0xbf8e3fb5,0xbec8bfb5,0x3ffb3f44,0x3f8e3fed,0x3ec8bfed,0x3fd53f44,
0xbff50000,0xbf710000,0x3f154000,0x3fe24000,0x3fa2bf8e,0xbfffbfd5,0xbfc6bfd5,0x3e493f8e,0xbe493fed,0xbfa2bfed,0x3fff3f44,0xbfc6bf44,
0xbf71bffb,0x3f15bec8,0xbfe23ec8,0xbff5bffb,0x3f444000,0x3fed4000,0x3fed0000,0x3f440000,0xbfedbfb5,0x3f443fb5,0xbf443fb5,0x3fed3fb5,
0x3fed0000,0xbf440000,0xbf44c000,0x3fed4000,0xbf443fb5,0xbfedbfb5,0x3fed3fb5,0x3f443fb5,0x3fe20000,0x3f150000,0xbf71c000,0xbff5c000,
0xbe493fd5,0x3fc63f8e,0x3fff3f8e,0xbfa2bfd5,0xbfc6bfed,0x3fff3fed,0xbfa23f44,0xbe49bf44,0x3ff53ec8,0x3fe23ffb,0xbf15bffb,0x3f713ec8,
0xbf8ec000,0xbffbc000,0xbfd50000,0xbec80000,0x3ffb3f44,0xbfd5bfed,0xbec8bfed,0xbf8ebf44,0xbec83fb5,0xbf8ebfb5,0x3ffb3fb5,0xbfd5bfb5,
0xbfd5bfed,0xbec8bf44,0xbf8e3f44,0xbffbbfed,0xbfc60000,0xbe490000,0x3fa24000,0x3fff4000,0xbf71bffb,0xbf15bec8,0xbfe2bec8,0x3ff53ffb,
0x3ff53f44,0xbf71bf44,0xbf15bfed,0x3fe23fed,0x3e493fd5,0xbfa2bf8e,0x3fff3f8e,0x3fc63fd5,0x40004000,0x3fb54000,0x0,0xbfb50000,
0x40004000,0xbfb50000,0x0,0xbfb5c000,0x40004000,0xbfb5c000,0x0,0x3fb50000,0x40004000,0x3fb50000,0x0,0x3fb54000,
0xbfc6bfb5,0xbfffbfb5,0xbfa2bfb5,0x3e49bfb5,0xbfe2bfd5,0x3f15bf8e,0xbf71bf8e,0x3ff53fd5,0xbff5bfed,0x3fe23fed,0xbf15bf44,0xbf713f44,
0xbfffbffb,0xbfa23ec8,0xbe49bec8,0xbfc6bffb,0x3ec80000,0x3fd50000,0x3ffb4000,0x3f8e4000,0x3f8e3f44,0x3ec83fed,0x3fd53fed,0xbffbbf44,
0x3fd53fb5,0xbffbbfb5,0x3f8e3fb5,0x3ec8bfb5,0x3ffb3fed,0x3f8ebf44,0x3ec83f44,0x3fd53fed,0x3f713fb5,0xbf153fb5,0xbfe2bfb5,0xbff5bfb5,
0xbe493ec8,0xbfa2bffb,0xbfffbffb,0x3fc6bec8,0xbfa2bf44,0x3fff3f44,0xbfc6bfed,0x3e493fed,0xbff5bfd5,0xbf713f8e,0xbf15bf8e,0xbfe2bfd5,
0xbfedc000,0xbf44c000,0x3f440000,0x3fed0000,0xbf44bfb5,0x3fed3fb5,0x3fed3fb5,0xbf443fb5,0x3f440000,0xbfed0000,0x3fed4000,0xbf44c000,
0x3fed3fb5,0x3f44bfb5,0x3f443fb5,0x3fed3fb5,0x3ff53fb5,0x3fe23fb5,0x3f153fb5,0xbf713fb5,0x3fc63ffb,0xbfffbec8,0xbfa2bec8,0xbe49bffb,
0xbe493f44,0x3fc6bf44,0xbfffbfed,0x3fa23fed,0xbfe2bf8e,0xbf153fd5,0xbf71bfd5,0xbff5bf8e,0xbf8e0000,0xbffb0000,0xbfd5c000,0xbec8c000,
0xbffbbfed,0x3fd5bf44,0x3ec8bf44,0x3f8e3fed,0xbec8bfb5,0xbf8e3fb5,0x3ffb3fb5,0xbfd5bfb5,0x3fd53f44,0x3ec8bfed,0x3f8e3fed,0x3ffb3f44,
0xbe49bfb5,0x3fa2bfb5,0x3fff3fb5,0x3fc63fb5,0x3ff53f8e,0xbf713fd5,0x3f153fd5,0xbfe2bf8e,0x3f713fed,0x3f15bfed,0xbfe2bf44,0x3ff53f44,
0xbfc6bec8,0xbe493ffb,0xbfa2bffb,0xbfffbec8,0x4000,0xbfb54000,0xc0000000,0xbfb50000,0xc000,0x3fb50000,0x40000000,0xbfb54000,
0x4000,0x3fb5c000,0xc0000000,0x3fb50000,0xc000,0xbfb50000,0x40000000,0x3fb5c000,0xbfa2bfb5,0x3e49bfb5,0x3fc6bfb5,0x3fffbfb5,
0x3f713fd5,0xbff53f8e,0xbfe23f8e,0x3f15bfd5,0xbf15bfed,0xbf713fed,0x3ff5bf44,0xbfe23f44,0x3e493ffb,0x3fc6bec8,0xbfff3ec8,0xbfa23ffb,
0x3ffb0000,0x3f8e0000,0xbec84000,0xbfd54000,0xbfd5bf44,0x3ffbbfed,0x3f8ebfed,0x3ec83f44,0x3f8e3fb5,0x3ec8bfb5,0xbfd53fb5,0x3ffbbfb5,
0xbec8bfed,0xbfd53f44,0x3ffbbf44,0x3f8ebfed,0xbfe23fb5,0xbff53fb5,0xbf71bfb5,0x3f15bfb5,0x3fffbec8,0xbfc63ffb,0xbe493ffb,0xbfa23ec8,
0xbfc6bf44,0x3e493f44,0x3fa2bfed,0xbfff3fed,0x3f153fd5,0x3fe2bf8e,0xbff53f8e,0xbf713fd5,0x3f44c000,0x3fedc000,0x3fed0000,0x3f440000,
0xbfed3fb5,0x3f44bfb5,0xbf44bfb5,0x3fedbfb5,0x3fed0000,0xbf440000,0xbf444000,0x3fedc000,0xbf44bfb5,0xbfed3fb5,0x3fedbfb5,0x3f44bfb5,
0x3f153fb5,0xbf713fb5,0xbff53fb5,0xbfe23fb5,0x3fa2bffb,0x3e493ec8,0x3fc63ec8,0xbfff3ffb,0xbfff3f44,0x3fa2bf44,0x3e49bfed,0xbfc63fed,
0x3f713f8e,0x3ff5bfd5,0xbfe23fd5,0xbf153f8e,0xbfd50000,0xbec80000,0x3f8ec000,0x3ffbc000,0xbec83fed,0xbf8e3f44,0xbffb3f44,0x3fd5bfed,
0x3ffbbfb5,0xbfd53fb5,0x3ec83fb5,0x3f8ebfb5,0xbf8ebf44,0xbffb3fed,0x3fd5bfed,0x3ec8bf44,0x3fffbfb5,0x3fc6bfb5,0x3e493fb5,0xbfa23fb5,
0xbf15bf8e,0x3fe2bfd5,0x3ff5bfd5,0xbf713f8e,0xbfe23fed,0x3ff5bfed,0xbf71bf44,0xbf153f44,0x3fa23ec8,0x3fffbffb,0xbfc63ffb,0xbe493ec8,
0xc0004000,0xbfb54000,0x0,0x3fb50000,0xc0004000,0x3fb50000,0x0,0x3fb5c000,0xc0004000,0x3fb5c000,0x0,0xbfb50000,
0xc0004000,0xbfb50000,0x0,0xbfb54000,0x3fc6bfb5,0x3fffbfb5,0x3fa2bfb5,0xbe49bfb5,0x3fe2bfd5,0xbf15bf8e,0x3f71bf8e,0xbff53fd5,
0x3ff5bfed,0xbfe23fed,0x3f15bf44,0x3f713f44,0x3fffbffb,0x3fa23ec8,0x3e49bec8,0x3fc6bffb,0xbec80000,0xbfd50000,0xbffb4000,0xbf8e4000,
0xbf8e3f44,0xbec83fed,0xbfd53fed,0x3ffbbf44,0xbfd53fb5,0x3ffbbfb5,0xbf8e3fb5,0xbec8bfb5,0xbffb3fed,0xbf8ebf44,0xbec83f44,0xbfd53fed,
0xbf713fb5,0x3f153fb5,0x3fe2bfb5,0x3ff5bfb5,0x3e493ec8,0x3fa2bffb,0x3fffbffb,0xbfc6bec8,0x3fa2bf44,0xbfff3f44,0x3fc6bfed,0xbe493fed,
0x3ff5bfd5,0x3f713f8e,0x3f15bf8e,0x3fe2bfd5,0x3fedc000,0x3f44c000,0xbf440000,0xbfed0000,0x3f44bfb5,0xbfed3fb5,0xbfed3fb5,0x3f443fb5,
0xbf440000,0x3fed0000,0xbfed4000,0x3f44c000,0xbfed3fb5,0xbf44bfb5,0xbf443fb5,0xbfed3fb5,0xbff53fb5,0xbfe23fb5,0xbf153fb5,0x3f713fb5,
0xbfc63ffb,0x3fffbec8,0x3fa2bec8,0x3e49bffb,0x3e493f44,0xbfc6bf44,0x3fffbfed,0xbfa23fed,0x3fe2bf8e,0x3f153fd5,0x3f71bfd5,0x3ff5bf8e,
0x3f8e0000,0x3ffb0000,0x3fd5c000,0x3ec8c000,0x3ffbbfed,0xbfd5bf44,0xbec8bf44,0xbf8e3fed,0x3ec8bfb5,0x3f8e3fb5,0xbffb3fb5,0x3fd5bfb5,
0xbfd53f44,0xbec8bfed,0xbf8e3fed,0xbffb3f44,0x3e49bfb5,0xbfa2bfb5,0xbfff3fb5,0xbfc63fb5,0xbff53f8e,0x3f713fd5,0xbf153fd5,0x3fe2bf8e,
0xbf713fed,0xbf15bfed,0x3fe2bf44,0xbff53f44,0x3fc6bec8,0x3e493ffb,0x3fa2bffb,0x3fffbec8,0x4000,0x3fb54000,0x40000000,0x3fb50000,
0xc000,0xbfb50000,0xc0000000,0x3fb54000,0x4000,0xbfb5c000,0x40000000,0xbfb50000,0xc000,0x3fb50000,0xc0000000,0xbfb5c000,
0x3fa2bfb5,0xbe49bfb5,0xbfc6bfb5,0xbfffbfb5,0xbf713fd5,0x3ff53f8e,0x3fe23f8e,0xbf15bfd5,0x3f15bfed,0x3f713fed,0xbff5bf44,0x3fe23f44,
0xbe493ffb,0xbfc6bec8,0x3fff3ec8,0x3fa23ffb,0xbffb0000,0xbf8e0000,0x3ec84000,0x3fd54000,0x3fd5bf44,0xbffbbfed,0xbf8ebfed,0xbec83f44,
0xbf8e3fb5,0xbec8bfb5,0x3fd53fb5,0xbffbbfb5,0x3ec8bfed,0x3fd53f44,0xbffbbf44,0xbf8ebfed,0x3fe23fb5,0x3ff53fb5,0x3f71bfb5,0xbf15bfb5,
0xbfffbec8,0x3fc63ffb,0x3e493ffb,0x3fa23ec8,0x3fc6bf44,0xbe493f44,0xbfa2bfed,0x3fff3fed,0xbf153fd5,0xbfe2bf8e,0x3ff53f8e,0x3f713fd5,
0xbf44c000,0xbfedc000,0xbfed0000,0xbf440000,0x3fed3fb5,0xbf44bfb5,0x3f44bfb5,0xbfedbfb5,0xbfed0000,0x3f440000,0x3f444000,0xbfedc000,
0x3f44bfb5,0x3fed3fb5,0xbfedbfb5,0xbf44bfb5,0xbf153fb5,0x3f713fb5,0x3ff53fb5,0x3fe23fb5,0xbfa2bffb,0xbe493ec8,0xbfc63ec8,0x3fff3ffb,
0x3fff3f44,0xbfa2bf44,0xbe49bfed,0x3fc63fed,0xbf713f8e,0xbff5bfd5,0x3fe23fd5,0x3f153f8e,0x3fd50000,0x3ec80000,0xbf8ec000,0xbffbc000,
0x3ec83fed,0x3f8e3f44,0x3ffb3f44,0xbfd5bfed,0xbffbbfb5,0x3fd53fb5,0xbec83fb5,0xbf8ebfb5,0x3f8ebf44,0x3ffb3fed,0xbfd5bfed,0xbec8bf44,
0xbfffbfb5,0xbfc6bfb5,0xbe493fb5,0x3fa23fb5,0x3f15bf8e,0xbfe2bfd5,0xbff5bfd5,0x3f713f8e,0x3fe23fed,0xbff5bfed,0x3f71bf44,0x3f153f44,
0xbfa23ec8,0xbfffbffb,0x3fc63ffb,0x3e493ec8,0x80003f80,0x3f800000,0x80003f80,0x3f800000,0x80003f80,0x3f800000,0x80003f80,0x3f800000,
0x80003f80,0x3f800000,0x80003f80,0x3f800000,0x80003f80,0x3f800000,0x80003f80,0x3f800000,0x80003f80,0x3f800000,0x8000bf80,0xbf800000,
0x3f353f35,0x3f35bf35,0xbf35bf35,0xbf353f35,0x3f800000,0xbf80,0xbf800000,0x3f80,0x3f35bf35,0xbf35bf35,0xbf353f35,0x3f353f35,
0x80003f80,0x3f800000,0x80003f80,0x3f800000,0x3f800000,0xbf80,0x3f800000,0xbf80,0x8000bf80,0xbf800000,0x8000bf80,0xbf800000,
0xbf800000,0x3f80,0xbf800000,0x3f80,0x80003f80,0x3f800000,0x8000bf80,0xbf800000,0x3f35bf35,0xbf35bf35,0xbf353f35,0x3f353f35,
0xbf800000,0x3f80,0x3f800000,0xbf80,0x3f353f35,0x3f35bf35,0xbf35bf35,0xbf353f35,0x80003f80,0x3f800000,0x80003f80,0x3f800000,
0x8000bf80,0xbf800000,0x8000bf80,0xbf800000,0x80003f80,0x3f800000,0x80003f80,0x3f800000,0x8000bf80,0xbf800000,0x8000bf80,0xbf800000,
0x80003f80,0x3f800000,0x8000bf80,0xbf800000,0xbf35bf35,0xbf353f35,0x3f353f35,0x3f35bf35,0x3f800000,0xbf80,0xbf800000,0x3f80,
0xbf353f35,0x3f353f35,0x3f35bf35,0xbf35bf35,0x80003f80,0x3f800000,0x80003f80,0x3f800000,0xbf800000,0x3f80,0xbf800000,0x3f80,
0x8000bf80,0xbf800000,0x8000bf80,0xbf800000,0x3f800000,0xbf80,0x3f800000,0xbf80,0x80003f80,0x3f800000,0x8000bf80,0xbf800000,
0xbf353f35,0x3f353f35,0x3f35bf35,0xbf35bf35,0xbf800000,0x3f80,0x3f800000,0xbf80,0xbf35bf35,0xbf353f35,0x3f353f35,0x3f35bf35,
0x3f803f80,0x80008000,0x80008000,0xbf80bf80,0x3f803f80,0x80008000,0x80008000,0xbf80bf80,0x3f803f80,0x80008000,0x80008000,0xbf80bf80,
0x3f803f80,0x80008000,0x80008000,0xbf80bf80,0x3f353f80,0x3f358000,0x3f358000,0xbf35bf80,0xbf350000,0x3f353f80,0x3f353f80,0x3f358000,
0xbf35bf80,0xbf358000,0xbf358000,0x3f353f80,0x3f350000,0xbf35bf80,0xbf35bf80,0xbf358000,0x3f80,0x3f808000,0x3f808000,0x8000bf80,
0xbf80,0xbf808000,0xbf808000,0x80003f80,0x3f80,0x3f808000,0x3f808000,0x8000bf80,0xbf80,0xbf808000,0xbf808000,0x80003f80,
0xbf353f80,0x3f358000,0x3f358000,0x3f35bf80,0x3f350000,0x3f35bf80,0x3f35bf80,0xbf358000,0x3f35bf80,0xbf358000,0xbf358000,0xbf353f80,
0xbf350000,0xbf353f80,0xbf353f80,0x3f358000,0xbf803f80,0x80008000,0x80008000,0x3f80bf80,0xbf803f80,0x80008000,0x80008000,0x3f80bf80,
0xbf803f80,0x80008000,0x80008000,0x3f80bf80,0xbf803f80,0x80008000,0x80008000,0x3f80bf80,0xbf353f80,0xbf358000,0xbf358000,0x3f35bf80,
0x3f350000,0xbf353f80,0xbf353f80,0xbf358000,0x3f35bf80,0x3f358000,0x3f358000,0xbf353f80,0xbf350000,0x3f35bf80,0x3f35bf80,0x3f358000,
0x3f80,0xbf808000,0xbf808000,0x8000bf80,0xbf80,0x3f808000,0x3f808000,0x80003f80,0x3f80,0xbf808000,0xbf808000,0x8000bf80,
0xbf80,0x3f808000,0x3f808000,0x80003f80,0x3f353f80,0xbf358000,0xbf358000,0xbf35bf80,0xbf350000,0xbf35bf80,0xbf35bf80,0x3f358000,
0xbf35bf80,0x3f358000,0x3f358000,0x3f353f80,0x3f350000,0x3f353f80,0x3f353f80,0xbf358000,0x3f800000,0x0,0x3f800000,0x0,
0x3f800000,0x0,0x3f800000,0x0,0x3f800000,0x0,0x3f800000,0x0,0x3f800000,0x0,0x3f800000,0x0,
0x3f800000,0x0,0x3f7fb10f,0xbd48fb30,0x3f7ec46d,0xbdc8bd36,0x3f7d3aac,0xbe164083,0x3f7b14be,0xbe47c5c2,0x3f7853f8,0xbe78cfcc,
0x3f74fa0b,0xbe94a031,0x3f710908,0xbeac7cd4,0x3f800000,0x0,0x3f7ec46d,0xbdc8bd36,0x3f7b14be,0xbe47c5c2,0x3f74fa0b,0xbe94a031,
0x3f6c835e,0xbec3ef15,0x3f61c598,0xbef15aea,0x3f54db31,0xbf0e39da,0x3f45e403,0xbf226799,0x3f800000,0x0,0x3f7d3aac,0xbe164083,
0x3f74fa0b,0xbe94a031,0x3f676bd8,0xbedae880,0x3f54db31,0xbf0e39da,0x3f3daef9,0xbf2beb4a,0x3f226799,0xbf45e403,0x3f039c3d,0xbf5b941a,
0x3f800000,0x0,0x3f7b14be,0xbe47c5c2,0x3f6c835e,0xbec3ef15,0x3f54db31,0xbf0e39da,0x3f3504f3,0xbf3504f3,0x3f0e39da,0xbf54db31,
0x3ec3ef15,0xbf6c835e,0x3e47c5c2,0xbf7b14be,0x3f800000,0x0,0x3f7853f8,0xbe78cfcc,0x3f61c598,0xbef15aea,0x3f3daef9,0xbf2beb4a,
0x3f0e39da,0xbf54db31,0x3eac7cd4,0xbf710908,0x3dc8bd36,0xbf7ec46d,0xbe164083,0xbf7d3aac,0x3f800000,0x0,0x3f74fa0b,0xbe94a031,
0x3f54db31,0xbf0e39da,0x3f226799,0xbf45e403,0x3ec3ef15,0xbf6c835e,0x3dc8bd36,0xbf7ec46d,0xbe47c5c2,0xbf7b14be,0xbef15aea,0xbf61c598,
0x3f800000,0x0,0x3f710908,0xbeac7cd4,0x3f45e403,0xbf226799,0x3f039c3d,0xbf5b941a,0x3e47c5c2,0xbf7b14be,0xbe164083,0xbf7d3aac,
0xbef15aea,0xbf61c598,0xbf3daef9,0xbf2beb4a,0x3f800000,0x0,0x3f800000,0x0,0x3f800000,0x0,0x3f800000,0x0,
0x3f800000,0x0,0x3f800000,0x0,0x3f800000,0x0,0x3f800000,0x0,0x3f6c835e,0xbec3ef15,0x3f676bd8,0xbedae880,
0x3f61c598,0xbef15aea,0x3f5b941a,0xbf039c3d,0x3f54db31,0xbf0e39da,0x3f4d9f02,0xbf187fc0,0x3f45e403,0xbf226799,0x3f3daef9,0xbf2beb4a,
0x3f3504f3,0xbf3504f3,0x3f226799,0xbf45e403,0x3f0e39da,0xbf54db31,0x3ef15aea,0xbf61c598,0x3ec3ef15,0xbf6c835e,0x3e94a031,0xbf74fa0b,
0x3e47c5c2,0xbf7b14be,0x3dc8bd36,0xbf7ec46d,0x3ec3ef15,0xbf6c835e,0x3e78cfcc,0xbf7853f8,0x3dc8bd36,0xbf7ec46d,0xbd48fb30,0xbf7fb10f,
0xbe47c5c2,0xbf7b14be,0xbeac7cd4,0xbf710908,0xbef15aea,0xbf61c598,0xbf187fc0,0xbf4d9f02,0x0,0xbf800000,0xbe47c5c2,0xbf7b14be,
0xbec3ef15,0xbf6c835e,0xbf0e39da,0xbf54db31,0xbf3504f3,0xbf3504f3,0xbf54db31,0xbf0e39da,0xbf6c835e,0xbec3ef15,0xbf7b14be,0xbe47c5c2,
0xbec3ef15,0xbf6c835e,0xbf187fc0,0xbf4d9f02,0xbf45e403,0xbf226799,0xbf676bd8,0xbedae880,0xbf7b14be,0xbe47c5c2,0xbf7fb10f,0x3d48fb30,
0xbf74fa0b,0x3e94a031,0xbf5b941a,0x3f039c3d,0xbf3504f3,0xbf3504f3,0xbf61c598,0xbef15aea,0xbf7b14be,0xbe47c5c2,0xbf7ec46d,0x3dc8bd36,
0xbf6c835e,0x3ec3ef15,0xbf45e403,0x3f226799,0xbf0e39da,0x3f54db31,0xbe94a031,0x3f74fa0b,0xbf6c835e,0xbec3ef15,0xbf7fb10f,0xbd48fb30,
0xbf74fa0b,0x3e94a031,0xbf4d9f02,0x3f187fc0,0xbf0e39da,0x3f54db31,0xbe78cfcc,0x3f7853f8,0x3dc8bd36,0x3f7ec46d,0x3edae880,0x3f676bd8,
0x80003f80,0x3f800000,0x3f800000,0xbf80,0x3ec43f6d,0x3f6dbec4,0x3f6dbec4,0xbec4bf6d,0x3f353f35,0x3f35bf35,0x3f35bf35,0xbf35bf35,
0x3f6d3ec4,0x3ec4bf6d,0x3ec4bf6d,0xbf6dbec4,0x80003f80,0x3f800000,0xbf800000,0x3f80,0x3f6d3ec4,0x3ec4bf6d,0xbec43f6d,0x3f6d3ec4,
0x3f35bf35,0xbf35bf35,0x3f353f35,0x3f35bf35,0xbec4bf6d,0xbf6d3ec4,0x3f6dbec4,0xbec4bf6d,0x80003f80,0x3f800000,0x3f800000,0xbf80,
0x3f6dbec4,0xbec4bf6d,0xbec4bf6d,0xbf6d3ec4,0xbf35bf35,0xbf353f35,0xbf353f35,0x3f353f35,0xbec43f6d,0x3f6d3ec4,0x3f6d3ec4,0x3ec4bf6d,
0x80003f80,0x3f800000,0xbf800000,0x3f80,0x3ec4bf6d,0xbf6dbec4,0x3f6d3ec4,0x3ec4bf6d,0xbf353f35,0x3f353f35,0xbf35bf35,0xbf353f35,
0x3f6dbec4,0xbec4bf6d,0x3ec43f6d,0x3f6dbec4,0x80003f80,0x3f800000,0x3f800000,0xbf80,0xbec4bf6d,0xbf6d3ec4,0xbf6d3ec4,0x3ec43f6d,
0x3f353f35,0x3f35bf35,0x3f35bf35,0xbf35bf35,0xbf6dbec4,0xbec43f6d,0xbec43f6d,0x3f6d3ec4,0x80003f80,0x3f800000,0xbf800000,0x3f80,
0xbf6dbec4,0xbec43f6d,0x3ec4bf6d,0xbf6dbec4,0x3f35bf35,0xbf35bf35,0x3f353f35,0x3f35bf35,0x3ec43f6d,0x3f6dbec4,0xbf6d3ec4,0x3ec43f6d,
0x80003f80,0x3f800000,0x3f800000,0xbf80,0xbf6d3ec4,0x3ec43f6d,0x3ec43f6d,0x3f6dbec4,0xbf35bf35,0xbf353f35,0xbf353f35,0x3f353f35,
0x3ec4bf6d,0xbf6dbec4,0xbf6dbec4,0xbec43f6d,0x80003f80,0x3f800000,0xbf800000,0x3f80,0xbec43f6d,0x3f6d3ec4,0xbf6dbec4,0xbec43f6d,
0xbf353f35,0x3f353f35,0xbf35bf35,0xbf353f35,0xbf6d3ec4,0x3ec43f6d,0xbec4bf6d,0xbf6d3ec4,0x3f803f80,0x80008000,0x80008000,0xbf80bf80,
0x3f803f80,0x80008000,0x80008000,0xbf80bf80,0x3f803f80,0x80008000,0x80008000,0xbf80bf80,0x3f803f80,0x80008000,0x80008000,0xbf80bf80,
0x3ec43f6d,0x3f6d3ec4,0x3f6d3ec4,0xbec4bf6d,0xbf6dbec4,0x3ec43f6d,0x3ec43f6d,0x3f6d3ec4,0xbec4bf6d,0xbf6dbec4,0xbf6dbec4,0x3ec43f6d,
0x3f6d3ec4,0xbec4bf6d,0xbec4bf6d,0xbf6dbec4,0xbf353f35,0x3f353f35,0x3f353f35,0x3f35bf35,0x3f35bf35,0xbf35bf35,0xbf35bf35,0xbf353f35,
0xbf353f35,0x3f353f35,0x3f353f35,0x3f35bf35,0x3f35bf35,0xbf35bf35,0xbf35bf35,0xbf353f35,0xbf6d3ec4,0xbec43f6d,0xbec43f6d,0x3f6dbec4,
0xbec43f6d,0x3f6dbec4,0x3f6dbec4,0x3ec4bf6d,0x3f6dbec4,0x3ec4bf6d,0x3ec4bf6d,0xbf6d3ec4,0x3ec4bf6d,0xbf6d3ec4,0xbf6d3ec4,0xbec43f6d,
0x0,0xbf803f80,0xbf803f80,0x80008000,0x0,0xbf803f80,0xbf803f80,0x80008000,0x0,0xbf803f80,0xbf803f80,0x80008000,
0x0,0xbf803f80,0xbf803f80,0x80008000,0x3f6dbec4,0xbec43f6d,0xbec43f6d,0xbf6d3ec4,0x3ec4bf6d,0x3f6dbec4,0x3f6dbec4,0xbec43f6d,
0xbf6d3ec4,0x3ec4bf6d,0x3ec4bf6d,0x3f6dbec4,0xbec43f6d,0xbf6d3ec4,0xbf6d3ec4,0x3ec4bf6d,0x3f35bf35,0x3f353f35,0x3f353f35,0xbf353f35,
0xbf353f35,0xbf35bf35,0xbf35bf35,0x3f35bf35,0x3f35bf35,0x3f353f35,0x3f353f35,0xbf353f35,0xbf353f35,0xbf35bf35,0xbf35bf35,0x3f35bf35,
0xbec4bf6d,0x3f6d3ec4,0x3f6d3ec4,0x3ec43f6d,0x3f6d3ec4,0x3ec43f6d,0x3ec43f6d,0xbf6dbec4,0x3ec43f6d,0xbf6dbec4,0xbf6dbec4,0xbec4bf6d,
0xbf6dbec4,0xbec4bf6d,0xbec4bf6d,0x3f6d3ec4,0x3f800000,0x0,0x3f7fec43,0xbcc90ab0,0x3f7fb10f,0xbd48fb30,0x3f7f4e6d,0xbd96a905,
0x3f7ec46d,0xbdc8bd36,0x3f7e1324,0xbdfab273,0x3f7d3aac,0xbe164083,0x3f7c3b28,0xbe2f10a2,0x3f800000,0x0,0x3f7f4e6d,0xbd96a905,
0x3f7d3aac,0xbe164083,0x3f79c79d,0xbe605c13,0x3f74fa0b,0xbe94a031,0x3f6ed89e,0xbeb8442a,0x3f676bd8,0xbedae880,0x3f5ebe05,0xbefc5d27,
0x3f800000,0x0,0x3f7e1324,0xbdfab273,0x3f7853f8,0xbe78cfcc,0x3f6ed89e,0xbeb8442a,0x3f61c598,0xbef15aea,0x3f514d3d,0xbf13682a,
0x3f3daef9,0xbf2beb4a,0x3f273656,0xbf41d870,0x3f800000,0x0,0x3f7c3b28,0xbe2f10a2,0x3f710908,0xbeac7cd4,0x3f5ebe05,0xbefc5d27,
0x3f45e403,0xbf226799,0x3f273656,0xbf41d870,0x3f039c3d,0xbf5b941a,0x3eb8442a,0xbf6ed89e,0x3f800000,0x0,0x3f79c79d,0xbe605c13,
0x3f676bd8,0xbedae880,0x3f49d112,0xbf1d7fd1,0x3f226799,0xbf45e403,0x3ee63375,0xbf64aa59,0x3e78cfcc,0xbf7853f8,0x3cc90ab0,0xbf7fec43,
0x3f800000,0x0,0x3f76ba07,0xbe888e93,0x3f5b941a,0xbf039c3d,0x3f3085bb,0xbf396842,0x3ef15aea,0xbf61c598,0x3e605c13,0xbf79c79d,
0xbd48fb30,0xbf7fb10f,0xbea09ae5,0xbf731447,0x3f800000,0x0,0x3f731447,0xbea09ae5,0x3f4d9f02,0xbf187fc0,0x3f13682a,0xbf514d3d,
0x3e94a031,0xbf74fa0b,0xbcc90ab0,0xbf7fec43,0xbeac7cd4,0xbf710908,0xbf1d7fd1,0xbf49d112,0x3f800000,0x0,0x3f6ed89e,0xbeb8442a,
0x3f3daef9,0xbf2beb4a,0x3ee63375,0xbf64aa59,0x3dc8bd36,0xbf7ec46d,0xbe888e93,0xbf76ba07,0xbf187fc0,0xbf4d9f02,0xbf584853,0xbf08f59b,
0x3f7b14be,0xbe47c5c2,0x3f79c79d,0xbe605c13,0x3f7853f8,0xbe78cfcc,0x3f76ba07,0xbe888e93,0x3f74fa0b,0xbe94a031,0x3f731447,0xbea09ae5,
0x3f710908,0xbeac7cd4,0x3f6ed89e,0xbeb8442a,0x3f54db31,0xbf0e39da,0x3f49d112,0xbf1d7fd1,0x3f3daef9,0xbf2beb4a,0x3f3085bb,0xbf396842,
0x3f226799,0xbf45e403,0x3f13682a,0xbf514d3d,0x3f039c3d,0xbf5b941a,0x3ee63375,0xbf64aa59,0x3f0e39da,0xbf54db31,0x3ee63375,0xbf64aa59,
0x3eac7cd4,0xbf710908,0x3e605c13,0xbf79c79d,0x3dc8bd36,0xbf7ec46d,0xbcc90ab0,0xbf7fec43,0xbe164083,0xbf7d3aac,0xbe888e93,0xbf76ba07,
0x3e47c5c2,0xbf7b14be,0x3cc90ab0,0xbf7fec43,0xbe164083,0xbf7d3aac,0xbea09ae5,0xbf731447,0xbef15aea,0xbf61c598,0xbf1d7fd1,0xbf49d112,
0xbf3daef9,0xbf2beb4a,0xbf584853,0xbf08f59b,0xbe47c5c2,0xbf7b14be,0xbecf7bca,0xbf6a09a7,0xbf187fc0,0xbf4d9f02,0xbf41d870,0xbf273656,
0xbf61c598,0xbef15aea,0xbf76ba07,0xbe888e93,0xbf7fb10f,0xbd48fb30,0xbf7c3b28,0x3e2f10a2,0xbf0e39da,0xbf54db31,0xbf41d870,0xbf273656,
0xbf676bd8,0xbedae880,0xbf7c3b28,0xbe2f10a2,0xbf7ec46d,0x3dc8bd36,0xbf6ed89e,0x3eb8442a,0xbf4d9f02,0x3f187fc0,0xbf1d7fd1,0x3f49d112,
0xbf54db31,0xbf0e39da,0xbf76ba07,0xbe888e93,0xbf7fb10f,0x3d48fb30,0xbf6ed89e,0x3eb8442a,0xbf45e403,0x3f226799,0xbf08f59b,0x3f584853,
0xbe78cfcc,0x3f7853f8,0x3d96a905,0x3f7f4e6d,0xbf7b14be,0xbe47c5c2,0xbf7c3b28,0x3e2f10a2,0xbf5b941a,0x3f039c3d,0xbf1d7fd1,0x3f49d112,
0xbe94a031,0x3f74fa0b,0x3d96a905,0x3f7f4e6d,0x3edae880,0x3f676bd8,0x3f396842,0x3f3085bb,0x80003f80,0x80003f80,0x80003f80,0x80003f80,
0x80003f80,0x80003f80,0x80003f80,0x80003f80,0x80003f80,0x80003f80,0x80003f80,0x80003f80,0x80003f80,0x80003f80,0x80003f80,0x80003f80,
0x3f800000,0x3f800000,0x3f800000,0x3f800000,0x3f800000,0x3f800000,0x3f800000,0x3f800000,0x3f800000,0x3f800000,0x3f800000,0x3f800000,
0x3f800000,0x3f800000,0x3f800000,0x3f800000,0x80003f80,0x3f353f35,0x80003f80,0x3f353f35,0x3f800000,0x3f35bf35,0x3f800000,0x3f35bf35,
0x8000bf80,0xbf35bf35,0x8000bf80,0xbf35bf35,0xbf800000,0xbf353f35,0xbf800000,0xbf353f35,0x3f800000,0x3f35bf35,0x3f800000,0x3f35bf35,
0xbf80,0xbf35bf35,0xbf80,0xbf35bf35,0xbf800000,0xbf353f35,0xbf800000,0xbf353f35,0x3f80,0x3f353f35,0x3f80,0x3f353f35,
0x80003f80,0x3f800000,0x80003f80,0x3f800000,0x8000bf80,0xbf800000,0x8000bf80,0xbf800000,0x80003f80,0x3f800000,0x80003f80,0x3f800000,
0x8000bf80,0xbf800000,0x8000bf80,0xbf800000,0x3f800000,0xbf80,0x3f800000,0xbf80,0xbf800000,0x3f80,0xbf800000,0x3f80,
0x3f800000,0xbf80,0x3f800000,0xbf80,0xbf800000,0x3f80,0xbf800000,0x3f80,0x80003f80,0x3f35bf35,0x80003f80,0x3f35bf35,
0xbf800000,0x3f353f35,0xbf800000,0x3f353f35,0x8000bf80,0xbf353f35,0x8000bf80,0xbf353f35,0x3f800000,0xbf35bf35,0x3f800000,0xbf35bf35,
0x3f800000,0xbf35bf35,0x3f800000,0xbf35bf35,0x3f80,0x3f35bf35,0x3f80,0x3f35bf35,0xbf800000,0x3f353f35,0xbf800000,0x3f353f35,
0xbf80,0xbf353f35,0xbf80,0xbf353f35,0x80003f80,0x3ec43f6d,0x8000bf80,0xbec4bf6d,0x3f353f35,0x3f6d3ec4,0xbf35bf35,0xbf6dbec4,
0x3f800000,0x3f6dbec4,0xbf800000,0xbf6d3ec4,0x3f35bf35,0x3ec4bf6d,0xbf353f35,0xbec43f6d,0x3f800000,0x3f6dbec4,0xbf800000,0xbf6d3ec4,
0x3f35bf35,0x3ec4bf6d,0xbf353f35,0xbec43f6d,0xbf80,0xbec4bf6d,0x3f80,0x3ec43f6d,0xbf35bf35,0xbf6dbec4,0x3f353f35,0x3f6d3ec4,
0x80003f80,0x3f6d3ec4,0x8000bf80,0xbf6dbec4,0x3f35bf35,0xbec4bf6d,0xbf353f35,0x3ec43f6d,0xbf800000,0xbec43f6d,0x3f800000,0x3ec4bf6d,
0x3f353f35,0x3f6dbec4,0xbf35bf35,0xbf6d3ec4,0x3f800000,0x3ec4bf6d,0xbf800000,0xbec43f6d,0xbf35bf35,0xbf6d3ec4,0x3f353f35,0x3f6dbec4,
0x3f80,0x3f6d3ec4,0xbf80,0xbf6dbec4,0x3f35bf35,0xbec4bf6d,0xbf353f35,0x3ec43f6d,0x80003f80,0x3f6dbec4,0x8000bf80,0xbf6d3ec4,
0xbf35bf35,0xbec43f6d,0x3f353f35,0x3ec4bf6d,0x3f800000,0xbec4bf6d,0xbf800000,0x3ec43f6d,0xbf353f35,0x3f6d3ec4,0x3f35bf35,0xbf6dbec4,
0x3f800000,0xbec4bf6d,0xbf800000,0x3ec43f6d,0xbf353f35,0x3f6d3ec4,0x3f35bf35,0xbf6dbec4,0xbf80,0xbf6d3ec4,0x3f80,0x3f6dbec4,
0x3f353f35,0x3ec4bf6d,0xbf35bf35,0xbec43f6d,0x80003f80,0x3ec4bf6d,0x8000bf80,0xbec43f6d,0xbf353f35,0x3f6dbec4,0x3f35bf35,0xbf6d3ec4,
0xbf800000,0x3f6d3ec4,0x3f800000,0xbf6dbec4,0xbf35bf35,0x3ec43f6d,0x3f353f35,0xbec4bf6d,0x3f800000,0xbf6dbec4,0xbf800000,0x3f6d3ec4,
0x3f353f35,0xbec4bf6d,0xbf35bf35,0x3ec43f6d,0x3f80,0x3ec4bf6d,0xbf80,0xbec43f6d,0xbf353f35,0x3f6dbec4,0x3f35bf35,0xbf6d3ec4,
0x80003f80,0x8000bf80,0x80003f80,0x8000bf80,0x80003f80,0x8000bf80,0x80003f80,0x8000bf80,0x80003f80,0x8000bf80,0x80003f80,0x8000bf80,
0x80003f80,0x8000bf80,0x80003f80,0x8000bf80,0x3f800000,0xbf800000,0x3f800000,0xbf800000,0x3f800000,0xbf800000,0x3f800000,0xbf800000,
0x3f800000,0xbf800000,0x3f800000,0xbf800000,0x3f800000,0xbf800000,0x3f800000,0xbf800000,0x80003f80,0xbf35bf35,0x80003f80,0xbf35bf35,
0x3f800000,0xbf353f35,0x3f800000,0xbf353f35,0x8000bf80,0x3f353f35,0x8000bf80,0x3f353f35,0xbf800000,0x3f35bf35,0xbf800000,0x3f35bf35,
0x3f800000,0xbf353f35,0x3f800000,0xbf353f35,0xbf80,0x3f353f35,0xbf80,0x3f353f35,0xbf800000,0x3f35bf35,0xbf800000,0x3f35bf35,
0x3f80,0xbf35bf35,0x3f80,0xbf35bf35,0x80003f80,0xbf800000,0x80003f80,0xbf800000,0x8000bf80,0x3f800000,0x8000bf80,0x3f800000,
0x80003f80,0xbf800000,0x80003f80,0xbf800000,0x8000bf80,0x3f800000,0x8000bf80,0x3f800000,0x3f800000,0x3f80,0x3f800000,0x3f80,
0xbf800000,0xbf80,0xbf800000,0xbf80,0x3f800000,0x3f80,0x3f800000,0x3f80,0xbf800000,0xbf80,0xbf800000,0xbf80,
0x80003f80,0xbf353f35,0x80003f80,0xbf353f35,0xbf800000,0xbf35bf35,0xbf800000,0xbf35bf35,0x8000bf80,0x3f35bf35,0x8000bf80,0x3f35bf35,
0x3f800000,0x3f353f35,0x3f800000,0x3f353f35,0x3f800000,0x3f353f35,0x3f800000,0x3f353f35,0x3f80,0xbf353f35,0x3f80,0xbf353f35,
0xbf800000,0xbf35bf35,0xbf800000,0xbf35bf35,0xbf80,0x3f35bf35,0xbf80,0x3f35bf35,0x80003f80,0xbec4bf6d,0x8000bf80,0x3ec43f6d,
0x3f353f35,0xbf6dbec4,0xbf35bf35,0x3f6d3ec4,0x3f800000,0xbf6d3ec4,0xbf800000,0x3f6dbec4,0x3f35bf35,0xbec43f6d,0xbf353f35,0x3ec4bf6d,
0x3f800000,0xbf6d3ec4,0xbf800000,0x3f6dbec4,0x3f35bf35,0xbec43f6d,0xbf353f35,0x3ec4bf6d,0xbf80,0x3ec43f6d,0x3f80,0xbec4bf6d,
0xbf35bf35,0x3f6d3ec4,0x3f353f35,0xbf6dbec4,0x80003f80,0xbf6dbec4,0x8000bf80,0x3f6d3ec4,0x3f35bf35,0x3ec43f6d,0xbf353f35,0xbec4bf6d,
0xbf800000,0x3ec4bf6d,0x3f800000,0xbec43f6d,0x3f353f35,0xbf6d3ec4,0xbf35bf35,0x3f6dbec4,0x3f800000,0xbec43f6d,0xbf800000,0x3ec4bf6d,
0xbf35bf35,0x3f6dbec4,0x3f353f35,0xbf6d3ec4,0x3f80,0xbf6dbec4,0xbf80,0x3f6d3ec4,0x3f35bf35,0x3ec43f6d,0xbf353f35,0xbec4bf6d,
0x80003f80,0xbf6d3ec4,0x8000bf80,0x3f6dbec4,0xbf35bf35,0x3ec4bf6d,0x3f353f35,0xbec43f6d,0x3f800000,0x3ec43f6d,0xbf800000,0xbec4bf6d,
0xbf353f35,0xbf6dbec4,0x3f35bf35,0x3f6d3ec4,0x3f800000,0x3ec43f6d,0xbf800000,0xbec4bf6d,0xbf353f35,0xbf6dbec4,0x3f35bf35,0x3f6d3ec4,
0xbf80,0x3f6dbec4,0x3f80,0xbf6d3ec4,0x3f353f35,0xbec43f6d,0xbf35bf35,0x3ec4bf6d,0x80003f80,0xbec43f6d,0x8000bf80,0x3ec4bf6d,
0xbf353f35,0xbf6d3ec4,0x3f35bf35,0x3f6dbec4,0xbf800000,0xbf6dbec4,0x3f800000,0x3f6d3ec4,0xbf35bf35,0xbec4bf6d,0x3f353f35,0x3ec43f6d,
0x3f800000,0x3f6d3ec4,0xbf800000,0xbf6dbec4,0x3f353f35,0x3ec43f6d,0xbf35bf35,0xbec4bf6d,0x3f80,0xbec43f6d,0xbf80,0x3ec4bf6d,
0xbf353f35,0xbf6d3ec4,0x3f35bf35,0x3f6dbec4,
};
constexpr int TB_F = 0, TB_E = 512, TB_P2 = 1024;

enum { C_EP = 0, C_Z1 = 32, C_Z2 = 96, C_H3 = 128, C_U = 160, C_X = 288, C_TOTAL = 512 };
struct Scratch {
  unsigned cnt[C_TOTAL];
  uint32_t moda[8 * 2 * D_];
  uint32_t mod[4 * D_ + 256];
  uint32_t z1[120 * 5120];
  uint32_t z2[128 * 4800];
  uint8_t h3[32 * 18 * 4096];
  uint8_t u[72 * D_ * 128];
};
__device__ __align__(1024) Scratch g_s;

#define HOLDA 5
#define GOAT 0
#define H3W 0
#define X1K 10
#define PEEK 1
#ifndef NV1
#define NV1 12
#endif
#ifndef NV2
#define NV2 20
#endif
#define GDEP 3
#define TRK0 50
#define W0N 3
#define TRKC 350
#define HD1 150
#define STRESS 0
#define GV 0
#define EH 7
#define RELK 2
#define KNOB0 0

#define FAILCNT(k) do {} while (0)
#define CK(k) do {} while (0)
#define CKX(k) do {} while (0)
#define TS(k) do {} while (0)
#define TSC(k) do {} while (0)
struct Maps { CUtensorMap z1, z2[2], w1a, w1b, h3, w2, wf[4], wm; };
struct Params {
  const __nv_bfloat16 *x, *c, *wmod;
  Scratch* s;
  const uint4* tab;
  const __nv_bfloat16 *wr, *wi, *w1, *w2, *b1, *b2;
  uint32_t* out;
};

__device__ __forceinline__ uint32_t smem_u32(const void* p) { return (uint32_t)__cvta_generic_to_shared(p); }
__device__ __forceinline__ void mbar_init(uint32_t b, int c) { asm volatile("mbarrier.init.shared::cta.b64 [%0], %1;" ::"r"(b), "r"(c)); }
__device__ __forceinline__ void mbar_expect(uint32_t b, int bytes) { asm volatile("mbarrier.arrive.expect_tx.shared::cta.b64 _, [%0], %1;" ::"r"(b), "r"(bytes) : "memory"); }
__device__ __forceinline__ void mbar_arrive(uint32_t b) { asm volatile("mbarrier.arrive.shared::cta.b64 _, [%0];" ::"r"(b) : "memory"); }
#define MBAR_WAIT(SEM)                                                                                                         \
  asm volatile("{\n.reg .pred p;\n.reg .u32 it;\nmov.u32 it, 0;\nW:\nmbarrier.try_wait.parity" SEM ".shared::cta.b64 p, [%0], %1;\n" \
               "@p bra.uni D;\nadd.u32 it, it, 1;\nsetp.lt.u32 p, it, 0x400000;\n@p bra.uni W;\ntrap;\nD:\n}" ::"r"(b), "r"(ph) : "memory")
__device__ __forceinline__ void mbar_wait(uint32_t b, int ph) { MBAR_WAIT(""); }
__device__ __forceinline__ uint32_t mbar_test(uint32_t b, int ph) {
  uint32_t ok;
  asm volatile("{\n.reg .pred p;\nmbarrier.test_wait.parity.shared::cta.b64 p, [%1], %2;\nselp.u32 %0, 1, 0, p;\n}\n" : "=r"(ok) : "r"(b), "r"(ph) : "memory");
  return ok;
}
__device__ __forceinline__ void tma2d(uint32_t dst, const CUtensorMap* m, int c0, int c1, uint32_t bar) {
  asm volatile("cp.async.bulk.tensor.2d.shared::cluster.global.mbarrier::complete_tx::bytes [%0], [%1, {%3, %4}], [%2];" ::"r"(dst), "l"(m), "r"(bar), "r"(c0), "r"(c1) : "memory");
}
__device__ __forceinline__ uint64_t pol_ef() { uint64_t p; asm("createpolicy.fractional.L2::evict_first.b64 %0, 1.0;" : "=l"(p)); return p; }
__device__ __forceinline__ void tma3d_ef(uint32_t dst, const CUtensorMap* m, int c1, int c2, uint32_t bar) {
  asm volatile("cp.async.bulk.tensor.3d.shared::cluster.global.mbarrier::complete_tx::bytes.L2::cache_hint [%0], [%1, {%3, %4, %5}], [%2], %6;" ::"r"(dst), "l"(m), "r"(bar), "r"(0), "r"(c1), "r"(c2), "l"(pol_ef()) : "memory");
}
__device__ __forceinline__ void tma4d_ef(uint32_t dst, const CUtensorMap* m, int c1, int c2, int c3, uint32_t bar) {
  asm volatile("cp.async.bulk.tensor.4d.shared::cluster.global.mbarrier::complete_tx::bytes.L2::cache_hint [%0], [%1, {%3, %7, %4, %5}], [%2], %6;" ::"r"(dst), "l"(m), "r"(bar), "r"(0), "r"(c2), "r"(c3), "l"(pol_ef()), "r"(c1) : "memory");
}
__device__ __forceinline__ void bulk_ld(uint32_t dst, const void* src, int bytes, uint32_t bar) {
  asm volatile("cp.async.bulk.shared::cluster.global.mbarrier::complete_tx::bytes [%0], [%1], %2, [%3];" ::"r"(dst), "l"(src), "r"(bytes), "r"(bar) : "memory");
}
__device__ __forceinline__ void bulk_st(void* dst, uint32_t src, int bytes) {
  asm volatile("cp.async.bulk.global.shared::cta.bulk_group [%0], [%1], %2;" ::"l"(dst), "r"(src), "r"(bytes) : "memory");
}
__device__ __forceinline__ void tma_st2d(const CUtensorMap* m, uint32_t src, int c0, int c1) {
  asm volatile("cp.async.bulk.tensor.2d.global.shared::cta.bulk_group [%0, {%2, %3}], [%1];" ::"l"(m), "r"(src), "r"(c0), "r"(c1) : "memory");
}
__device__ __forceinline__ void tma_st3d(const CUtensorMap* m, uint32_t src, int c0, int c1, int c2) {
  asm volatile("cp.async.bulk.tensor.3d.global.shared::cta.bulk_group [%0, {%2, %3, %4}], [%1];" ::"l"(m), "r"(src), "r"(c0), "r"(c1), "r"(c2) : "memory");
}
__device__ __forceinline__ void bulk_commit_wait_read() {
  asm volatile("cp.async.bulk.commit_group;" ::: "memory");
  asm volatile("cp.async.bulk.wait_group.read 0;" ::: "memory");
}
__device__ __forceinline__ void bulk_commit_wait() {
  asm volatile("cp.async.bulk.commit_group;" ::: "memory");
  asm volatile("cp.async.bulk.wait_group 0;" ::: "memory");
}
__device__ __forceinline__ void prefetch_l2(const void* p, int bytes) {
  asm volatile("cp.async.bulk.prefetch.L2.global [%0], %1;" ::"l"(p), "r"(bytes) : "memory");
}
__device__ __forceinline__ void wg_fence() { asm volatile("wgmma.fence.sync.aligned;" ::: "memory"); }
__device__ __forceinline__ void wg_commit() { asm volatile("wgmma.commit_group.sync.aligned;" ::: "memory"); }
template <int N> __device__ __forceinline__ void wg_wait() { asm volatile("wgmma.wait_group.sync.aligned %0;" ::"n"(N) : "memory"); }
template <int N> __device__ __forceinline__ void reg_fence(float (&d)[N]) {
#pragma unroll
  for (int i = 0; i < N; i++) asm volatile("" : "+f"(d[i])::"memory");
}
__device__ __forceinline__ void fence_async_smem() { asm volatile("fence.proxy.async.shared::cta;" ::: "memory"); }
__device__ __forceinline__ void fence_async_glb() { asm volatile("fence.proxy.async.global;" ::: "memory"); }
__device__ __forceinline__ uint32_t ld_rlx(const void* p) { uint32_t v; asm volatile("ld.relaxed.gpu.global.b32 %0, [%1];" : "=r"(v) : "l"(p) : "memory"); return v; }
__device__ __forceinline__ uint2 ld_rlx2(const void* p) { uint2 v; asm volatile("ld.relaxed.gpu.global.v2.b32 {%0,%1}, [%2];" : "=r"(v.x), "=r"(v.y) : "l"(p) : "memory"); return v; }
__device__ __forceinline__ uint4 ld_rlx4(const void* p) { uint4 v; asm volatile("ld.relaxed.gpu.global.v4.b32 {%0,%1,%2,%3}, [%4];" : "=r"(v.x), "=r"(v.y), "=r"(v.z), "=r"(v.w) : "l"(p) : "memory"); return v; }
__device__ __forceinline__ uint32_t ld_nc(const void* p) { uint32_t v; asm volatile("ld.global.nc.L1::no_allocate.b32 %0, [%1];" : "=r"(v) : "l"(p) : "memory"); return v; }
__device__ __forceinline__ uint4 ld_nc4(const void* p) { uint4 v; asm volatile("ld.global.nc.v4.b32 {%0,%1,%2,%3}, [%4];" : "=r"(v.x), "=r"(v.y), "=r"(v.z), "=r"(v.w) : "l"(p) : "memory"); return v; }
__device__ __forceinline__ uint32_t lds(uint32_t a) { uint32_t v; asm volatile("ld.shared.b32 %0, [%1];" : "=r"(v) : "r"(a) : "memory"); return v; }
__device__ __forceinline__ uint2 lds2(uint32_t a) { uint2 v; asm volatile("ld.shared.v2.b32 {%0,%1}, [%2];" : "=r"(v.x), "=r"(v.y) : "r"(a) : "memory"); return v; }
__device__ __forceinline__ void lds2_if(int on, uint2& v, uint32_t a) { asm volatile("{\n.reg .pred p;\nsetp.ne.u32 p, %3, 0;\n@p ld.shared.v2.b32 {%0,%1}, [%2];\n}" : "+r"(v.x), "+r"(v.y) : "r"(a), "r"(on) : "memory"); }
__device__ __forceinline__ uint4 lds4(uint32_t a) { uint4 v; asm volatile("ld.shared.v4.b32 {%0,%1,%2,%3}, [%4];" : "=r"(v.x), "=r"(v.y), "=r"(v.z), "=r"(v.w) : "r"(a) : "memory"); return v; }
__device__ __forceinline__ float lds_bf(uint32_t a) { uint32_t v; asm volatile("ld.shared.u16 %0, [%1];" : "=r"(v) : "r"(a) : "memory"); return __uint_as_float(v << 16); }
__device__ __forceinline__ void sts(uint32_t a, uint32_t v) { asm volatile("st.shared.b32 [%0], %1;" ::"r"(a), "r"(v) : "memory"); }
__device__ __forceinline__ void sts2(uint32_t a, uint32_t v0, uint32_t v1) { asm volatile("st.shared.v2.b32 [%0], {%1,%2};" ::"r"(a), "r"(v0), "r"(v1) : "memory"); }
__device__ __forceinline__ void sts4(uint32_t a, uint32_t v0, uint32_t v1, uint32_t v2, uint32_t v3) { asm volatile("st.shared.v4.b32 [%0], {%1,%2,%3,%4};" ::"r"(a), "r"(v0), "r"(v1), "r"(v2), "r"(v3) : "memory"); }
__device__ __forceinline__ void bar_sync(int id, int n) { asm volatile("bar.sync %0, %1;" ::"r"(id), "r"(n) : "memory"); }
__device__ __forceinline__ void bar_arrive(int id, int n) { asm volatile("bar.arrive %0, %1;" ::"r"(id), "r"(n) : "memory"); }
__device__ __forceinline__ void red_add(unsigned* p, unsigned v) { asm volatile("red.relaxed.gpu.global.add.u32 [%0], %1;" ::"l"(p), "r"(v) : "memory"); }
__device__ __forceinline__ bool any(bool p) { return __any_sync(0xffffffffu, p); }
__device__ __forceinline__ void pause(unsigned clks) {
  asm volatile("{\n.reg .pred p;\n.reg .u32 a, b;\nmov.u32 a, %%clock;\nW:\nmov.u32 b, %%clock;\nsub.u32 b, b, a;\nsetp.lt.s32 p, b, %0;\n@p bra.uni W;\n}" ::"r"(clks) : "memory");
}
__device__ __forceinline__ void red_bf16x8(uint32_t* p, uint32_t a, uint32_t b, uint32_t c, uint32_t d) {
  asm volatile("red.relaxed.gpu.global.add.noftz.v4.bf16x2 [%0], {%1,%2,%3,%4};" ::"l"(p), "r"(a), "r"(b), "r"(c), "r"(d) : "memory");
}
__device__ __forceinline__ void red_bf16x4(uint32_t* p, uint32_t a, uint32_t b) {
  asm volatile("red.relaxed.gpu.global.add.noftz.v2.bf16x2 [%0], {%1,%2};" ::"l"(p), "r"(a), "r"(b) : "memory");
}
constexpr int SPIN_MAX = 1 << 20;
__device__ __forceinline__ uint32_t ld_acq(const void* p) { uint32_t v; asm volatile("ld.acquire.gpu.global.b32 %0, [%1];" : "=r"(v) : "l"(p) : "memory"); return v; }
template <bool ACQ = false> __device__ __forceinline__ void wait_cnt(const unsigned* p, unsigned target) {
  int it = 0;
  while (any((int)((ACQ ? ld_acq(p) : ld_rlx(p)) - target) < 0) && ++it < SPIN_MAX) {}
}
__device__ __forceinline__ uint32_t pack_bf16(float lo, float hi) { uint32_t r; asm("cvt.rn.bf16x2.f32 %0, %1, %2;" : "=r"(r) : "f"(hi), "f"(lo)); return r; }
__device__ __forceinline__ float bf_lo(uint32_t v) { return __uint_as_float(v << 16); }
__device__ __forceinline__ float bf_hi(uint32_t v) { return __uint_as_float(v & 0xffff0000u); }
__device__ __forceinline__ uint32_t hadd2(uint32_t a, uint32_t b) { uint32_t r; asm("add.rn.bf16x2 %0, %1, %2;" : "=r"(r) : "r"(a), "r"(b)); return r; }
__device__ __forceinline__ uint32_t hmul2(uint32_t a, uint32_t b) { uint32_t r; asm("mul.rn.bf16x2 %0, %1, %2;" : "=r"(r) : "r"(a), "r"(b)); return r; }
__device__ __forceinline__ uint32_t hfma2(uint32_t a, uint32_t b, uint32_t c) { uint32_t r; asm("fma.rn.bf16x2 %0, %1, %2, %3;" : "=r"(r) : "r"(a), "r"(b), "r"(c)); return r; }
__device__ __forceinline__ float rbf(float x) { uint32_t r; asm("cvt.rn.bf16x2.f32 %0, %1, %2;" : "=r"(r) : "f"(x), "f"(0.0f)); return __uint_as_float(r); }
__device__ __forceinline__ void stmatrix4(uint32_t a, uint32_t r0, uint32_t r1, uint32_t r2, uint32_t r3) {
  asm volatile("stmatrix.sync.aligned.m8n8.x4.shared.b16 [%0], {%1,%2,%3,%4};" ::"r"(a), "r"(r0), "r"(r1), "r"(r2), "r"(r3) : "memory");
}
__device__ __forceinline__ void stmatrix2(uint32_t a, uint32_t r0, uint32_t r1) {
  asm volatile("stmatrix.sync.aligned.m8n8.x2.shared.b16 [%0], {%1,%2};" ::"r"(a), "r"(r0), "r"(r1) : "memory");
}
__device__ __forceinline__ uint32_t movm(uint32_t a) { uint32_t r; asm("movmatrix.sync.aligned.m8n8.trans.b16 %0, %1;" : "=r"(r) : "r"(a)); return r; }
template <bool ACC> __device__ __forceinline__ void mma16(float* d, uint32_t a0, uint32_t a1, uint32_t a2, uint32_t a3, uint32_t b0, uint32_t b1) {
  if (ACC) asm("mma.sync.aligned.m16n8k16.row.col.f32.bf16.bf16.f32 {%0,%1,%2,%3}, {%4,%5,%6,%7}, {%8,%9}, {%0,%1,%2,%3};"
               : "+f"(d[0]), "+f"(d[1]), "+f"(d[2]), "+f"(d[3]) : "r"(a0), "r"(a1), "r"(a2), "r"(a3), "r"(b0), "r"(b1));
  else asm("mma.sync.aligned.m16n8k16.row.col.f32.bf16.bf16.f32 {%0,%1,%2,%3}, {%4,%5,%6,%7}, {%8,%9}, {%10,%10,%10,%10};"
           : "=f"(d[0]), "=f"(d[1]), "=f"(d[2]), "=f"(d[3]) : "r"(a0), "r"(a1), "r"(a2), "r"(a3), "r"(b0), "r"(b1), "f"(0.f));
}
__device__ __forceinline__ uint32_t pin(uint32_t v) { uint32_t r; asm volatile("shfl.sync.bfly.b32 %0, %1, 0, 31, 0xffffffff;" : "=r"(r) : "r"(v)); return r; }
template <class T> __device__ __forceinline__ T* pin(T* p) {
  const uint64_t a = reinterpret_cast<uint64_t>(p);
  return reinterpret_cast<T*>((uint64_t)pin((uint32_t)a) | ((uint64_t)pin((uint32_t)(a >> 32)) << 32));
}
__device__ __forceinline__ uint32_t upin(uint32_t v) { return __shfl_sync(0xffffffffu, v, 0); }
template <class T> __device__ __forceinline__ T* upin(T* p) {
  const uint64_t a = reinterpret_cast<uint64_t>(p);
  return reinterpret_cast<T*>((uint64_t)upin((uint32_t)a) | ((uint64_t)upin((uint32_t)(a >> 32)) << 32));
}
__device__ __forceinline__ bool elect() {
  uint32_t p;
  asm volatile("{\n.reg .pred P;\nelect.sync _|P, 0xffffffff;\nselp.u32 %0, 1, 0, P;\n}" : "=r"(p));
  return p;
}
__device__ __forceinline__ uint32_t set_tag(uint32_t w, uint32_t tag) { uint32_t r; asm("lop3.b32 %0, %1, 0xfffffffe, %2, 0xea;" : "=r"(r) : "r"(w), "r"(tag)); return r; }
__device__ __forceinline__ uint32_t bitsel(uint32_t w, uint32_t m, uint32_t o) { uint32_t r; asm("lop3.b32 %0, %1, %2, %3, 0xe2;" : "=r"(r) : "r"(w), "r"(m), "r"(o)); return r; }
__device__ __forceinline__ uint32_t or3(uint32_t a, uint32_t b, uint32_t c) { uint32_t r; asm("lop3.b32 %0, %1, %2, %3, 0xfe;" : "=r"(r) : "r"(a), "r"(b), "r"(c)); return r; }
__device__ __forceinline__ uint32_t diff2(uint32_t a, uint32_t b, uint32_t tag) { uint32_t r; asm("lop3.b32 %0, %1, %2, %3, 0x7e;" : "=r"(r) : "r"(a), "r"(b), "r"(tag)); return r; }
__device__ __forceinline__ float2 cmul(float2 a, float2 b) { return make_float2(a.x * b.x - a.y * b.y, a.x * b.y + a.y * b.x); }

template<int TB> __device__ __forceinline__ void wgmma_ss_160_0(float (&d)[96], uint32_t al, uint32_t ah, uint32_t bl, uint32_t bh) {
  asm volatile("{\n.reg .b64 da, db;\nmov.b64 da, {%80, %81};\nmov.b64 db, {%82, %83};\n"
    "wgmma.mma_async.sync.aligned.m64n160k16.f32.bf16.bf16 {%0,%1,%2,%3,%4,%5,%6,%7,%8,%9,%10,%11,%12,%13,%14,%15,%16,%17,%18,%19,%20,%21,%22,%23,%24,%25,%26,%27,%28,%29,%30,%31,%32,%33,%34,%35,%36,%37,%38,%39,%40,%41,%42,%43,%44,%45,%46,%47,%48,%49,%50,%51,%52,%53,%54,%55,%56,%57,%58,%59,%60,%61,%62,%63,%64,%65,%66,%67,%68,%69,%70,%71,%72,%73,%74,%75,%76,%77,%78,%79}, da, db, 1, 1, 1, 1, %84;\n}\n"
    : "+f"(d[0]),"+f"(d[1]),"+f"(d[2]),"+f"(d[3]),"+f"(d[4]),"+f"(d[5]),"+f"(d[6]),"+f"(d[7]),"+f"(d[8]),"+f"(d[9]),"+f"(d[10]),"+f"(d[11]),"+f"(d[12]),"+f"(d[13]),"+f"(d[14]),"+f"(d[15]),"+f"(d[16]),"+f"(d[17]),"+f"(d[18]),"+f"(d[19]),"+f"(d[20]),"+f"(d[21]),"+f"(d[22]),"+f"(d[23]),"+f"(d[24]),"+f"(d[25]),"+f"(d[26]),"+f"(d[27]),"+f"(d[28]),"+f"(d[29]),"+f"(d[30]),"+f"(d[31]),"+f"(d[32]),"+f"(d[33]),"+f"(d[34]),"+f"(d[35]),"+f"(d[36]),"+f"(d[37]),"+f"(d[38]),"+f"(d[39]),"+f"(d[40]),"+f"(d[41]),"+f"(d[42]),"+f"(d[43]),"+f"(d[44]),"+f"(d[45]),"+f"(d[46]),"+f"(d[47]),"+f"(d[48]),"+f"(d[49]),"+f"(d[50]),"+f"(d[51]),"+f"(d[52]),"+f"(d[53]),"+f"(d[54]),"+f"(d[55]),"+f"(d[56]),"+f"(d[57]),"+f"(d[58]),"+f"(d[59]),"+f"(d[60]),"+f"(d[61]),"+f"(d[62]),"+f"(d[63]),"+f"(d[64]),"+f"(d[65]),"+f"(d[66]),"+f"(d[67]),"+f"(d[68]),"+f"(d[69]),"+f"(d[70]),"+f"(d[71]),"+f"(d[72]),"+f"(d[73]),"+f"(d[74]),"+f"(d[75]),"+f"(d[76]),"+f"(d[77]),"+f"(d[78]),"+f"(d[79])
    : "r"(al), "r"(ah), "r"(bl), "r"(bh), "n"(TB));
}
template<int TB> __device__ __forceinline__ void wgmma_ss_144_0(float (&d)[96], uint32_t al, uint32_t ah, uint32_t bl, uint32_t bh) {
  asm volatile("{\n.reg .b64 da, db;\nmov.b64 da, {%72, %73};\nmov.b64 db, {%74, %75};\n"
    "wgmma.mma_async.sync.aligned.m64n144k16.f32.bf16.bf16 {%0,%1,%2,%3,%4,%5,%6,%7,%8,%9,%10,%11,%12,%13,%14,%15,%16,%17,%18,%19,%20,%21,%22,%23,%24,%25,%26,%27,%28,%29,%30,%31,%32,%33,%34,%35,%36,%37,%38,%39,%40,%41,%42,%43,%44,%45,%46,%47,%48,%49,%50,%51,%52,%53,%54,%55,%56,%57,%58,%59,%60,%61,%62,%63,%64,%65,%66,%67,%68,%69,%70,%71}, da, db, 1, 1, 1, 1, %76;\n}\n"
    : "+f"(d[0]),"+f"(d[1]),"+f"(d[2]),"+f"(d[3]),"+f"(d[4]),"+f"(d[5]),"+f"(d[6]),"+f"(d[7]),"+f"(d[8]),"+f"(d[9]),"+f"(d[10]),"+f"(d[11]),"+f"(d[12]),"+f"(d[13]),"+f"(d[14]),"+f"(d[15]),"+f"(d[16]),"+f"(d[17]),"+f"(d[18]),"+f"(d[19]),"+f"(d[20]),"+f"(d[21]),"+f"(d[22]),"+f"(d[23]),"+f"(d[24]),"+f"(d[25]),"+f"(d[26]),"+f"(d[27]),"+f"(d[28]),"+f"(d[29]),"+f"(d[30]),"+f"(d[31]),"+f"(d[32]),"+f"(d[33]),"+f"(d[34]),"+f"(d[35]),"+f"(d[36]),"+f"(d[37]),"+f"(d[38]),"+f"(d[39]),"+f"(d[40]),"+f"(d[41]),"+f"(d[42]),"+f"(d[43]),"+f"(d[44]),"+f"(d[45]),"+f"(d[46]),"+f"(d[47]),"+f"(d[48]),"+f"(d[49]),"+f"(d[50]),"+f"(d[51]),"+f"(d[52]),"+f"(d[53]),"+f"(d[54]),"+f"(d[55]),"+f"(d[56]),"+f"(d[57]),"+f"(d[58]),"+f"(d[59]),"+f"(d[60]),"+f"(d[61]),"+f"(d[62]),"+f"(d[63]),"+f"(d[64]),"+f"(d[65]),"+f"(d[66]),"+f"(d[67]),"+f"(d[68]),"+f"(d[69]),"+f"(d[70]),"+f"(d[71])
    : "r"(al), "r"(ah), "r"(bl), "r"(bh), "n"(TB));
}
template<int TB> __device__ __forceinline__ void wgmma_ss_96_0(float (&d)[96], uint32_t al, uint32_t ah, uint32_t bl, uint32_t bh) {
  asm volatile("{\n.reg .b64 da, db;\nmov.b64 da, {%48, %49};\nmov.b64 db, {%50, %51};\n"
    "wgmma.mma_async.sync.aligned.m64n96k16.f32.bf16.bf16 {%0,%1,%2,%3,%4,%5,%6,%7,%8,%9,%10,%11,%12,%13,%14,%15,%16,%17,%18,%19,%20,%21,%22,%23,%24,%25,%26,%27,%28,%29,%30,%31,%32,%33,%34,%35,%36,%37,%38,%39,%40,%41,%42,%43,%44,%45,%46,%47}, da, db, 1, 1, 1, 1, %52;\n}\n"
    : "+f"(d[0]),"+f"(d[1]),"+f"(d[2]),"+f"(d[3]),"+f"(d[4]),"+f"(d[5]),"+f"(d[6]),"+f"(d[7]),"+f"(d[8]),"+f"(d[9]),"+f"(d[10]),"+f"(d[11]),"+f"(d[12]),"+f"(d[13]),"+f"(d[14]),"+f"(d[15]),"+f"(d[16]),"+f"(d[17]),"+f"(d[18]),"+f"(d[19]),"+f"(d[20]),"+f"(d[21]),"+f"(d[22]),"+f"(d[23]),"+f"(d[24]),"+f"(d[25]),"+f"(d[26]),"+f"(d[27]),"+f"(d[28]),"+f"(d[29]),"+f"(d[30]),"+f"(d[31]),"+f"(d[32]),"+f"(d[33]),"+f"(d[34]),"+f"(d[35]),"+f"(d[36]),"+f"(d[37]),"+f"(d[38]),"+f"(d[39]),"+f"(d[40]),"+f"(d[41]),"+f"(d[42]),"+f"(d[43]),"+f"(d[44]),"+f"(d[45]),"+f"(d[46]),"+f"(d[47])
    : "r"(al), "r"(ah), "r"(bl), "r"(bh), "n"(TB));
}
template<int TB> __device__ __forceinline__ void wgmma_ss_96_48(float (&d)[96], uint32_t al, uint32_t ah, uint32_t bl, uint32_t bh) {
  asm volatile("{\n.reg .b64 da, db;\nmov.b64 da, {%48, %49};\nmov.b64 db, {%50, %51};\n"
    "wgmma.mma_async.sync.aligned.m64n96k16.f32.bf16.bf16 {%0,%1,%2,%3,%4,%5,%6,%7,%8,%9,%10,%11,%12,%13,%14,%15,%16,%17,%18,%19,%20,%21,%22,%23,%24,%25,%26,%27,%28,%29,%30,%31,%32,%33,%34,%35,%36,%37,%38,%39,%40,%41,%42,%43,%44,%45,%46,%47}, da, db, 1, 1, 1, 1, %52;\n}\n"
    : "+f"(d[48]),"+f"(d[49]),"+f"(d[50]),"+f"(d[51]),"+f"(d[52]),"+f"(d[53]),"+f"(d[54]),"+f"(d[55]),"+f"(d[56]),"+f"(d[57]),"+f"(d[58]),"+f"(d[59]),"+f"(d[60]),"+f"(d[61]),"+f"(d[62]),"+f"(d[63]),"+f"(d[64]),"+f"(d[65]),"+f"(d[66]),"+f"(d[67]),"+f"(d[68]),"+f"(d[69]),"+f"(d[70]),"+f"(d[71]),"+f"(d[72]),"+f"(d[73]),"+f"(d[74]),"+f"(d[75]),"+f"(d[76]),"+f"(d[77]),"+f"(d[78]),"+f"(d[79]),"+f"(d[80]),"+f"(d[81]),"+f"(d[82]),"+f"(d[83]),"+f"(d[84]),"+f"(d[85]),"+f"(d[86]),"+f"(d[87]),"+f"(d[88]),"+f"(d[89]),"+f"(d[90]),"+f"(d[91]),"+f"(d[92]),"+f"(d[93]),"+f"(d[94]),"+f"(d[95])
    : "r"(al), "r"(ah), "r"(bl), "r"(bh), "n"(TB));
}
__device__ __forceinline__ void wgmma_rs_72(float (&d)[36], uint32_t a0, uint32_t a1, uint32_t a2, uint32_t a3, uint32_t bl, uint32_t bh, int sd) {
  asm volatile("{\n.reg .pred p;\n.reg .b64 db;\nsetp.ne.b32 p, %42, 0;\nmov.b64 db, {%40, %41};\n"
    "wgmma.mma_async.sync.aligned.m64n72k16.f32.bf16.bf16 {%0,%1,%2,%3,%4,%5,%6,%7,%8,%9,%10,%11,%12,%13,%14,%15,%16,%17,%18,%19,%20,%21,%22,%23,%24,%25,%26,%27,%28,%29,%30,%31,%32,%33,%34,%35}, {%36,%37,%38,%39}, db, p, 1, 1, 1;\n}\n"
    : "+f"(d[0]),"+f"(d[1]),"+f"(d[2]),"+f"(d[3]),"+f"(d[4]),"+f"(d[5]),"+f"(d[6]),"+f"(d[7]),"+f"(d[8]),"+f"(d[9]),"+f"(d[10]),"+f"(d[11]),"+f"(d[12]),"+f"(d[13]),"+f"(d[14]),"+f"(d[15]),"+f"(d[16]),"+f"(d[17]),"+f"(d[18]),"+f"(d[19]),"+f"(d[20]),"+f"(d[21]),"+f"(d[22]),"+f"(d[23]),"+f"(d[24]),"+f"(d[25]),"+f"(d[26]),"+f"(d[27]),"+f"(d[28]),"+f"(d[29]),"+f"(d[30]),"+f"(d[31]),"+f"(d[32]),"+f"(d[33]),"+f"(d[34]),"+f"(d[35])
    : "r"(a0), "r"(a1), "r"(a2), "r"(a3), "r"(bl), "r"(bh), "r"(sd));
}
__device__ __forceinline__ void wgmma_rs_48(float (&d)[24], uint32_t a0, uint32_t a1, uint32_t a2, uint32_t a3, uint32_t bl, uint32_t bh, int sd) {
  asm volatile("{\n.reg .pred p;\n.reg .b64 db;\nsetp.ne.b32 p, %30, 0;\nmov.b64 db, {%28, %29};\n"
    "wgmma.mma_async.sync.aligned.m64n48k16.f32.bf16.bf16 {%0,%1,%2,%3,%4,%5,%6,%7,%8,%9,%10,%11,%12,%13,%14,%15,%16,%17,%18,%19,%20,%21,%22,%23}, {%24,%25,%26,%27}, db, p, 1, 1, 1;\n}\n"
    : "+f"(d[0]),"+f"(d[1]),"+f"(d[2]),"+f"(d[3]),"+f"(d[4]),"+f"(d[5]),"+f"(d[6]),"+f"(d[7]),"+f"(d[8]),"+f"(d[9]),"+f"(d[10]),"+f"(d[11]),"+f"(d[12]),"+f"(d[13]),"+f"(d[14]),"+f"(d[15]),"+f"(d[16]),"+f"(d[17]),"+f"(d[18]),"+f"(d[19]),"+f"(d[20]),"+f"(d[21]),"+f"(d[22]),"+f"(d[23])
    : "r"(a0), "r"(a1), "r"(a2), "r"(a3), "r"(bl), "r"(bh), "r"(sd));
}
template<int N,int OFF,int TB> __device__ __forceinline__ void wgmma_ss(float (&d)[96], uint32_t al, uint32_t ah, uint32_t bl, uint32_t bh) {
  if constexpr (N==160 && OFF==0) wgmma_ss_160_0<TB>(d, al, ah, bl, bh);
  else if constexpr (N==144 && OFF==0) wgmma_ss_144_0<TB>(d, al, ah, bl, bh);
  else if constexpr (N==96 && OFF==0) wgmma_ss_96_0<TB>(d, al, ah, bl, bh);
  else if constexpr (N==96 && OFF==48) wgmma_ss_96_48<TB>(d, al, ah, bl, bh);
}

__device__ __forceinline__ void dft3(float2& a, float2& b, float2& c) {
  const float s = 0.86602540378443864676f;
  float2 t = make_float2(b.x + c.x, b.y + c.y), d = make_float2(b.x - c.x, b.y - c.y);
  float2 m = make_float2(fmaf(-0.5f, t.x, a.x), fmaf(-0.5f, t.y, a.y));
  a = make_float2(a.x + t.x, a.y + t.y);
  b = make_float2(fmaf(s, d.y, m.x), fmaf(-s, d.x, m.y));
  c = make_float2(fmaf(-s, d.y, m.x), fmaf(s, d.x, m.y));
}
__device__ __forceinline__ void dft9(float2 (&x)[9]) {
  const float2 w1 = make_float2(0.76604444311897803520f, -0.64278760968653932632f);
  const float2 w2 = make_float2(0.17364817766693034885f, -0.98480775301220805937f);
  const float2 w4 = make_float2(-0.93969262078590838405f, -0.34202014332566873304f);
  dft3(x[0], x[3], x[6]); dft3(x[1], x[4], x[7]); dft3(x[2], x[5], x[8]);
  x[4] = cmul(x[4], w1); x[7] = cmul(x[7], w2); x[5] = cmul(x[5], w2); x[8] = cmul(x[8], w4);
  dft3(x[0], x[1], x[2]); dft3(x[3], x[4], x[5]); dft3(x[6], x[7], x[8]);
  float2 t;
  t = x[1]; x[1] = x[3]; x[3] = t;
  t = x[2]; x[2] = x[6]; x[6] = t;
  t = x[5]; x[5] = x[7]; x[7] = t;
}

__device__ __forceinline__ uint32_t* mod_ptr(Scratch* sc, int u, int t128) {
  const int i = t128 & 15;
  return u < 72 ? sc->moda + (t128 >> 4) * (2 * D_) + 16 * u + 2 * (i & 7) + (i >> 3) : sc->mod + 16 * (u - 72) + i;
}
__device__ __forceinline__ void mod_unit(Scratch* sc, int u, int t128, uint32_t sw_, uint32_t bar, int ph, uint32_t rb, uint32_t tag) {
  const int w = t128 >> 5, l = t128 & 31;
  uint32_t b[18];
#pragma unroll
  for (int i = 0; i < 18; i++) b[i] = lds(red + 512 + (72 * w + 4 * i + (l & 3)) * 4);
  const uint32_t sa = pin(sw_ + (144 * w + (l & 7) + 8 * (l >> 4)) * 32 + (((l >> 3) ^ (l >> 2)) & 1) * 16);
  const uint32_t sr = pin(rb + (l >> 2) * 16 + w * 4);
  uint32_t* const dst = pin(mod_ptr(sc, u, t128));
  const int kind = u / 36;
  const float mul = __uint_as_float(pin(__float_as_uint(kind == 0 ? 16.0f : 1.0f))), add = __uint_as_float(pin(__float_as_uint(kind == 1 || kind == 4 ? 1.0f : 0.0f)));
  mbar_wait(bar, ph);
  if (t128 == 0 && u < 72) TS(10);
  float d[3][4];
#pragma unroll
  for (int i = 0; i < 9; i++) {
    uint32_t a0, a1, a2, a3;
    asm volatile("ldmatrix.sync.aligned.m8n8.x4.trans.shared.b16 {%0,%1,%2,%3}, [%4];" : "=r"(a0), "=r"(a1), "=r"(a2), "=r"(a3) : "r"(sa + i * 512) : "memory");
    if (i < 3) mma16<false>(d[i], a0, a1, a2, a3, b[2 * i], b[2 * i + 1]);
    else mma16<true>(d[i % 3], a0, a1, a2, a3, b[2 * i], b[2 * i + 1]);
  }
  if ((l & 3) == 0) { sts(sr, __float_as_uint(d[0][0] + d[1][0] + d[2][0])); sts(sr + 128, __float_as_uint(d[0][2] + d[1][2] + d[2][2])); }
  bar_sync(4, 128);
  const uint4 v = lds4(rb + (l & 15) * 16);
  const float m = rbf(fmaf(rbf((__uint_as_float(v.x) + __uint_as_float(v.y)) + (__uint_as_float(v.z) + __uint_as_float(v.w))), mul, add));
  if (u < 72 || t128 < 16) *dst = __float_as_uint(m) | tag;
}

__device__ __forceinline__ float rsq(float x) { float r; asm("rsqrt.approx.ftz.f32 %0, %1;" : "=f"(r) : "f"(x)); return r; }
__device__ __forceinline__ void ln_stats2(const float (&a)[18], const float (&b)[18], float sc, float& oa, float& ra, float& ob, float& rb) {
  float v[4] = {0.f, 0.f, 0.f, 0.f}, w[4] = {0.f, 0.f, 0.f, 0.f};
#pragma unroll
  for (int i = 0; i < 18; i += 2) {
    v[0] += a[i]; v[1] = fmaf(a[i], a[i], v[1]); v[2] += b[i]; v[3] = fmaf(b[i], b[i], v[3]);
    w[0] += a[i + 1]; w[1] = fmaf(a[i + 1], a[i + 1], w[1]); w[2] += b[i + 1]; w[3] = fmaf(b[i + 1], b[i + 1], w[3]);
  }
#pragma unroll
  for (int e = 0; e < 4; e++) v[e] += w[e];
#pragma unroll
  for (int o = 16; o; o >>= 1) {
#pragma unroll
    for (int e = 0; e < 4; e++) v[e] += __shfl_xor_sync(0xffffffffu, v[e], o);
  }
  const float ma = v[0] * (1.0f / D_), mb = v[2] * (1.0f / D_);
  ra = sc * rsq(fmaxf(fmaf(-ma, ma, v[1] * (1.0f / D_)), 0.f) + 1e-5f);
  rb = sc * rsq(fmaxf(fmaf(-mb, mb, v[3] * (1.0f / D_)), 0.f) + 1e-5f);
  oa = -ma * ra; ob = -mb * rb;
}

__device__ __forceinline__ void ln_stats1(const float (&a)[18], float sc, float& oa, float& ra) {
  float v[3] = {a[0], a[1], a[2]}, w[3] = {a[0] * a[0], a[1] * a[1], a[2] * a[2]};
#pragma unroll
  for (int i = 3; i < 18; i++) { v[i % 3] += a[i]; w[i % 3] = fmaf(a[i], a[i], w[i % 3]); }
  float s = v[0] + v[1] + v[2], q = w[0] + w[1] + w[2];
#pragma unroll
  for (int o = 16; o; o >>= 1) { s += __shfl_xor_sync(0xffffffffu, s, o); q += __shfl_xor_sync(0xffffffffu, q, o); }
  const float m = s * (1.0f / D_);
  ra = sc * rsq(fmaxf(fmaf(-m, m, q * (1.0f / D_)), 0.f) + 1e-5f);
  oa = -m * ra;
}

__device__ __forceinline__ float tmat(int c, int q, int j) {
  const int ph = q == 1 ? 1024 * j : (q >> 1) * (c + 128 * j) + 512 * (q & 1);
  return __cosf((float)(((ph + 1024) & 2047) - 1024) * (6.283185307179586f / 2048.0f));
}
__device__ __forceinline__ uint32_t line_off(int k1, int kap, int pi, int f) {
  int kd = 64 * k1 + 9 * kap;
  if (kap == 0 && k1 > 4) kd -= 288;
  if (kd >= D_) kd -= D_;
  return pi * 2400 + ((min(kd, D_ - kd) ^ f) << 3);
}

struct Ring { uint32_t st, ph; };
template <bool G2, class T> __device__ __forceinline__ void ring_next(T& st, T& ph) {
  if (++st == NST) st = 0;
  ph ^= ((G2 ? 0xDu : 0x1u) >> st) & 1;
}
__device__ __forceinline__ void arrive_if(uint32_t a, uint32_t p) {
  asm volatile("{\n.reg .pred p;\nsetp.ne.u32 p, %1, 0;\n@p mbarrier.arrive.shared::cta.b64 _, [%0];\n}" ::"r"(a), "r"(p) : "memory");
}
template <int NA> __device__ __forceinline__ void reg_fence_n(float (&d)[96]) {
#pragma unroll
  for (int i = 0; i < NA; i++) asm volatile("" : "+f"(d[i])::"memory");
}
template <int MODE>
__device__ __forceinline__ void gemm_main(float (&acc)[96], uint32_t da0, uint32_t da1, uint32_t db0, int wg, Ring& rg,
                                          bool rows, int J, uint32_t* x1p, const uint32_t (&xr)[18]) {
  constexpr int NKB = MODE == 3 ? 36 : 32;
  constexpr uint32_t HA = 0x40000040u, HB = MODE == 3 ? 0xC0000010u : 0x80000020u;
  constexpr uint32_t KA = 2048 >> 4, KB = (MODE == 3 ? 512 : 1024) >> 4;
  constexpr int NA = MODE == 3 ? 72 : MODE == 1 ? 96 : 80;
  const uint32_t t = threadIdx.x & 127;
  const uint32_t eb = full0 + 8 * NST;
  uint32_t pb = 0, prel = 0, ok = 0;
  int n = MODE != 3 ? X1K + 2 * wg : wg ? NKB - J : NKB, nh = 0, ng = MODE == 3 && !wg;
#pragma unroll 1
  for (int pass = MODE == 3 ? 0 : -1;; pass++) {
#pragma unroll 1
    do {
      const uint32_t so = rg.st * ((MODE == 3 ? STAGE2 : STAGE) >> 4), cb = eb + 8 * rg.st;
      if (__builtin_expect(!ok, 0)) mbar_wait(full0 + 8 * rg.st, rg.ph);
      reg_fence_n<NA>(acc);
      if (MODE == 1 && wg) {
        wg_fence();
#pragma unroll
        for (int k = 0; k < 4; k++) wgmma_ss<96, 48, 1>(acc, da1 + so + k * KA, HA, db0 + so + k * KB, HB);
        wg_commit();
      }
      wg_fence();
#pragma unroll
      for (int k = 0; k < 4; k++) {
        if (k == RELK) asm volatile("{\n.reg .pred p;\nsetp.eq.s32 p, %0, %1;\n@p bar.arrive 1, 256;\n}" ::"r"(n), "r"(ng) : "memory");
        if (k == 3) { ring_next<MODE == 3>(rg.st, rg.ph); ok = PEEK ? mbar_test(full0 + 8 * rg.st, rg.ph) : 0; }
        if (MODE == 0) wgmma_ss<160, 0, 1>(acc, da0 + so + k * KA, HA, db0 + so + k * KB, HB);
        else if (MODE == 3) wgmma_ss<144, 0, 1>(acc, da0 + so + k * KA, HA, db0 + so + k * KB, HB);
        else wgmma_ss<96, 0, 1>(acc, da0 + so + k * KA, HA, db0 + so + k * KB, HB);
      }
      wg_commit();
      wg_wait<1>();
      reg_fence_n<NA>(acc);
      arrive_if(pb, prel);
      pb = cb; prel = t == 0 && (MODE != 0 || n != nh);
    } while (--n);
    if (pass == wg) break;
    if (MODE != 3 && pass < 0) {
      if (rows) {
#pragma unroll
        for (int i = 0; i < 9; i++) { x1p[32 * i] = xr[i]; x1p[512 * 288 + 32 * i] = xr[9 + i]; }
      }
      n = NKB - X1K - (J + 2) * wg;
      if (!wg) { ng = 1; if (J < NST) nh = NST; }
      continue;
    }
    wg_wait<0>();
    arrive_if(pb, prel);
    prel = 0;
    n = J;
    if (MODE == 0 && J < NST) bar_arrive(11, 256);
    bar_sync(1, 256);
  }
  if (MODE == 0 && J < NST && !wg) bar_sync(11, 256);
  wg_wait<0>();
  reg_fence_n<NA>(acc);
  if (MODE != 3) arrive_if(pb, prel);
}

constexpr float GK1 = 2.0f * 0.7978845608028654f, GK3 = 8.0f * 0.044715f * 0.7978845608028654f;

__device__ __forceinline__ int kb2_order(int i) { const int wv = i / 6; return 6 * (i - 6 * wv) + ((0x431250 >> (4 * wv)) & 7); }

__device__ __forceinline__ int kb2_pos(int kb) { const int hf = kb >= 36, k = kb - 36 * hf, gr = k / 6; return 64 * hf + gr + 6 * ((0x154230 >> (4 * (k - 6 * gr))) & 7); }

__device__ __forceinline__ void wait_flags(const unsigned* p, int idx, unsigned target, uint32_t& ready) {
  int it = 0;
  while (!((ready >> idx) & 1) && it++ < SPIN_MAX) ready = __ballot_sync(0xffffffffu, (int)(ld_rlx(p) - target) >= 0);
}

enum { B_FULL = 0, B_EMPTY = 6, B_S4 = 12, B_S5, B_LAND, B_FLT = B_LAND + 6, B_Z1, B_Z2, B_GO, B_X, B_WM, B_NUM, B_W0 = B_NUM };

__global__ void __launch_bounds__(NTHR, 1)
fused_kernel(const Params p, const __grid_constant__ Maps maps) {
  extern __shared__ __align__(1024) uint8_t smem_raw[];
  const int bx = blockIdx.x, cta = bx < 112 || bx >= 130 ? bx : bx < 114 ? bx + 16 : bx - 2;
  const int tid = threadIdx.x, t128 = tid & 127;
  const int wp = __shfl_sync(0xffffffffu, tid >> 5, 0), wg = wp >> 2;
  const int l = tid & 31, g = l >> 2, t = l & 3;
  Scratch* const sc = p.s;
  const bool rows = cta < 128;
  const int mu = rows ? cta + 4 : cta - 128;
  const int R = mu - 12;

  uint32_t xr[18];
  uint32_t cv[3];
  const unsigned ep0 = ld_rlx(&sc->cnt[C_EP + l]);
  if (tid == 0) TS(0);
  if (wg == 2) {
#pragma unroll
    for (int i = 0; i < 3; i++) cv[i] = ld_nc(reinterpret_cast<const uint32_t*>(p.c) + min(t128 + 128 * i, 287));
    if (wp == 9 && l < 9 && rows) {
      const int h = 9 * cta + l;
      prefetch_l2(reinterpret_cast<const uint8_t*>(p.wmod) + (size_t)(h >> 1) * (12 * D_) + (h & 1) * (2 * D_), 2 * D_);
    }
    if (tid == 256 && mu < 72) {
      mbar_init(full0 + 8 * B_W0, 1);
      fence_async_smem();
      mbar_expect(full0 + 8 * B_W0, 18432);
#pragma unroll 1
      for (int i = 0; i < 3; i++) tma2d(sbase + O_P2 + i * 6144, &maps.wm, 16 * mu, 192 * i, full0 + 8 * B_W0);
    }
    __syncwarp();
#pragma unroll 1
    for (int u = mu < 72 ? mu : 72 + mu; u < 216; u += u < 72 ? 72 : NCTA) if (u < 72 || t128 < 16) *mod_ptr(sc, u, t128) = 0;
    if (wp == 11 && smem_u32(smem_raw) != sbase) __trap();
    if (wp >= 10 && elect()) {
#pragma unroll 1
      for (int i = wp - 10; i < B_NUM; i += 2) mbar_init(full0 + 8 * i, i == B_FLT ? 4 : i == B_WM ? 3 : i < B_S4 ? 2 : 1);
      fence_async_smem();
    }
    __syncwarp();
  } else if (rows) {
    const uint32_t* xs = reinterpret_cast<const uint32_t*>(p.x) + (size_t)(cta + 128 * ((wp & 3) + 8 * wg)) * 288 + l;
#pragma unroll
    for (int i = 0; i < 9; i++) { xr[i] = ld_nc(xs + 32 * i); xr[9 + i] = ld_nc(xs + 512 * 288 + 32 * i); }
  }
  CK(0);
  if (tid == 64 && cta == NCTA - 1) prefetch_l2(p.tab, sizeof(T_TAB));
  __syncwarp();
  auto tag_of = [](unsigned e) { return (e & 0x7fffu) | 0x8000u; };
  const int kap = 8 * ((wp & 3) ^ (wg & 1)) + g;
  uint32_t tb[4], sb1[3], lo[9];
#pragma unroll
  for (int i = 0; i < 4; i++) tb[i] = pin(pack_bf16(tmat(cta, 8 * (i >> 1) + g, t + 8 * (i & 1)), tmat(cta, 8 * (i >> 1) + g, t + 8 * (i & 1) + 4)));
#pragma unroll
  for (int i = 0; i < 3; i++) {
    const int d = 48 * wp + 16 * i + (l & 15);
    sb1[i] = pin(sbase + O_B1 + (l >> 4) * 9216 + (d % 9) * 1024 + (d & 63) * 16);
  }
#pragma unroll
  for (int k1 = 0; k1 < 9; k1++) lo[k1] = pin(sbase + O_Z1 + line_off(k1, kap, 4 * wg + t, cta & 3));
  const uint32_t snt = pin(sbase + O_NRM + ((l & 7) + 8 * (l >> 4)) * 1168 + (48 * wp + (l & 8)) * 2), sn = pin(sbase + O_NRM + wp * 2336 + l * 4);
  const uint32_t smask = pin(t ? 0u : 0xffff0000u);
  const uint32_t* const mp = pin(sc->moda + (cta >> 4) * (2 * D_) + 48 * wp + 2 * g);
  const uint4* const ftab = pin(p.tab + TB_F + (t128 ^ (wg << 5)));

  if (wg == 2) {
#pragma unroll
    for (int i = 0; i < 3; i++) {
      const float c0 = bf_lo(cv[i]), c1 = bf_hi(cv[i]);
      sts(red + 512 + min(t128 + 128 * i, 287) * 4, pack_bf16(__fdividef(c0, 1.0f + __expf(-c0)), __fdividef(c1, 1.0f + __expf(-c1))));
    }
    if (t128 == 0) sts(full0 + 248, ep0 + 1);
    if (wp == 9 && l < 11) asm volatile("prefetch.tensormap [%0];" ::"l"(&maps.z1 + l) : "memory");
    bar_sync(4, 128);
    if (mu < 72) {
      mod_unit(sc, mu, t128, sbase + O_P2, full0 + 8 * B_W0, 0, red, tag_of(upin(ep0) + 1));
      if (t128 == 0) TS(25);
    }
    CK(1);
  }
  const int pi = R / 15, col0 = 20 * (R - 15 * pi);
  const int xu = DF_ * pi + col0, xv = DF_ * (pi ? 16 - pi : 8) + col0;
  auto load_filter = [&](int a) {
    const int x = (a & 1) ? xv : xu;
    const bool wide = (x & 15) > 12;
    mbar_expect(full0 + 8 * B_FLT, wide ? 12288 : 8192);
    tma2d(sbase + O_RAW + a * 12288, &maps.wf[a & 2], x & ~15, 0, full0 + 8 * B_FLT);
    if (wide) tma2d(sbase + O_RAW + a * 12288 + 8192, &maps.wf[(a & 2) + 1], (x & ~15) + 32, 0, full0 + 8 * B_FLT);
  };
  uint4 af[4];
  if (rows) {
    uint2 ms[3], mc[3];
    auto load_mod = [&](uint32_t o = 0) {
#pragma unroll
      for (int i = 0; i < 3; i++) { ms[i] = ld_rlx2(mp + 2 * o + 16 * i); mc[i] = ld_rlx2(mp + 2 * o + D_ + 16 * i); }
    };
    if (wg < 2) {
      float a[18], b[18];
#pragma unroll
      for (int i = 0; i < 9; i++) { a[2 * i] = bf_lo(xr[i]); a[2 * i + 1] = bf_hi(xr[i]); b[2 * i] = bf_lo(xr[9 + i]); b[2 * i + 1] = bf_hi(xr[9 + i]); }
      float oa, ra, ob, rb;
      ln_stats2(a, b, 1.0f, oa, ra, ob, rb);
      CK(1);
      load_mod((__float_as_uint(ra) | __float_as_uint(rb)) >> 31);
#pragma unroll
      for (int i = 0; i < 9; i++) {
        sts(sn + i * 128, pack_bf16(fmaf(a[2 * i], ra, oa), fmaf(a[2 * i + 1], ra, oa)));
        sts(sn + 1168 + i * 128, pack_bf16(fmaf(b[2 * i], rb, ob), fmaf(b[2 * i + 1], rb, ob)));
      }
      CK(2);
      bar_arrive(10, NTHR);
#pragma unroll
      for (int kk = 0; kk < 4; kk++) af[kk] = ld_nc4(ftab + kk * 128);
      bar_sync(1, 256);
      if (tid == 0) TS(2);
    } else {
      bar_sync(10, NTHR);
      load_mod();
      CK(2);
      if (wp >= 10 && elect()) prefetch_l2(reinterpret_cast<const uint8_t*>(wp == 10 ? p.wr : p.wi) + cta * 9248, 9248);
      __syncwarp();
    }
    float rs[3][8];
#pragma unroll
    for (int i = 0; i < 3; i++) {
      uint32_t a0, a1, a2, a3;
      asm volatile("ldmatrix.sync.aligned.m8n8.x4.trans.shared.b16 {%0,%1,%2,%3}, [%4];" : "=r"(a0), "=r"(a1), "=r"(a2), "=r"(a3)
                   : "r"(snt + 32 * i) : "memory");
      mma16<false>(&rs[i][0], a0, a1, a2, a3, tb[0], tb[1]);
      mma16<false>(&rs[i][4], a0, a1, a2, a3, tb[2], tb[3]);
    }
    CK(3);
    const uint32_t tag16 = tag_of(upin(ep0) + 1), tag1 = tag16 & 1;
    {
      int it = 0;
#pragma unroll 1
      while (true) {
        uint32_t bad = 0;
#pragma unroll
        for (int i = 0; i < 3; i++) bad |= diff2(ms[i].x, ms[i].y, tag16) | diff2(mc[i].x, mc[i].y, tag16);
        if (!any(bad & 0xffffu) || ++it > SPIN_MAX) break;
        load_mod();
      }
      CK(4);
      if (tid == 0) TS(3);
#pragma unroll
      for (int i = 0; i < 3; i++) {
        const float c0 = bf_hi(mc[i].x), c1 = bf_hi(mc[i].y);
        const float s0 = __uint_as_float(ms[i].x & smask), s1 = __uint_as_float(ms[i].y & smask);
        stmatrix4(sb1[i], pack_bf16(fmaf(rs[i][0], c0, s0), rs[i][1] * c0), pack_bf16(fmaf(rs[i][2], c1, s1), rs[i][3] * c1),
                  pack_bf16(rs[i][4] * c0, rs[i][5] * c0), pack_bf16(rs[i][6] * c1, rs[i][7] * c1));
      }
    }
    fence_async_smem();
    CK(5);
    if (wg == 2) {
      bar_arrive(5, NTHR);
      if (R >= 0 && elect()) load_filter(wp - 8);
      __syncwarp();
      const int slot = 4 * (cta & 7) + ((cta >> 4) & 3) + 32 * (2 * (cta >> 6) + ((cta >> 3) & 1));
      const uint32_t c0 = upin(40 * slot), c1 = upin(60 * (wp & 1)), src = upin(sbase + O_Z1 + (wp & 1) * 9600);
      const CUtensorMap* mz = upin(&maps.z1);
      unsigned* hint = pin(sc->cnt + C_Z1 + 32 * (wp & 1));
      if (wp < 10) {
        bar_sync(2 + (wp & 1), 160);
        if (elect()) tma_st2d(mz, src, c0, c1);
        pause(HD1);
        if (elect()) red_add(hint, 1);
        bulk_commit_wait();
        if (tid == 256) TS(4);
        __syncwarp();
      }
    } else {
      bar_sync(5, NTHR);
      CK(6);
      float acc[36];
      const uint32_t db = (((sbase + O_B1 + wg * 9216) & 0x3FFFF) >> 4) | ((128 >> 4) << 16);
      wg_fence();
#pragma unroll
      for (int kk = 0; kk < 4; kk++) wgmma_rs_72(acc, af[kk].x, af[kk].y, af[kk].z, af[kk].w, db + kk * 16, 1024 >> 4, kk);
      wg_commit();
      wg_wait<0>();
      reg_fence(acc);
      CK(7);
      float2 za[9], zb[9];
#pragma unroll
      for (int i = 0; i < 9; i++) { za[i] = make_float2(acc[4 * i], acc[4 * i + 2]); zb[i] = make_float2(acc[4 * i + 1], acc[4 * i + 3]); }
      dft9(za); dft9(zb);
      if ((wp & 3) == wg) {
        const float sp = g ? 0.f : 1.f;
#pragma unroll
        for (int k = 1; k < 5; k++) {
          float2 a = za[k], b = za[9 - k];
          za[k] = make_float2(fmaf(sp, b.x, a.x), fmaf(-sp, b.y, a.y)); za[9 - k] = make_float2(fmaf(-sp, a.x, b.x), fmaf(sp, a.y, b.y));
          a = zb[k]; b = zb[9 - k];
          zb[k] = make_float2(fmaf(sp, b.x, a.x), fmaf(-sp, b.y, a.y)); zb[9 - k] = make_float2(fmaf(-sp, a.x, b.x), fmaf(sp, a.y, b.y));
        }
        const uint32_t w0 = set_tag(pack_bf16(za[0].y, 0.f), tag1), w1 = pack_bf16(zb[0].y, 0.f);
        asm volatile("{\n.reg .pred p;\nsetp.eq.u32 p, %3, 0;\n@p st.shared.v2.b32 [%0], {%1,%2};\n}" ::"r"(lo[0] + 288 * 8), "r"(w0), "r"(w1), "r"(g) : "memory");
        za[0].y = g ? za[0].y : 0.f; zb[0].y = g ? zb[0].y : 0.f;
      }
#pragma unroll
      for (int k1 = 0; k1 < 9; k1++) sts2(lo[k1], set_tag(pack_bf16(za[k1].x, za[k1].y), tag1), pack_bf16(zb[k1].x, zb[k1].y));
      fence_async_smem();
      CK(8);
      bar_arrive(2 + wg, 160);
      {
        const uint32_t fx = (((cta >> 4) ^ cta) & 3) << 3, dl = O_IN - O_Z1, st = sbase + O_ST + 15360 + tid * 16;
        sts4(st, (lo[0] ^ fx) + dl, (lo[1] ^ fx) + dl, (lo[2] ^ fx) + dl, (lo[3] ^ fx) + dl);
        sts4(st + 4096, (lo[4] ^ fx) + dl, (lo[5] ^ fx) + dl, (lo[6] ^ fx) + dl, (lo[7] ^ fx) + dl);
        sts4(st + 8192, (lo[8] ^ fx) + dl, (lo[0] ^ fx) + dl + (kap ? 0 : 288 * 8),
             sbase + O_B3 + wg * 1024 + (l >> 4) * 2048 + (2 * (kap & 24) + (l & 15)) * 16, 0);
      }
    }
    {
      uint32_t sy[6];
#pragma unroll
      for (int i = 0; i < 6; i++) {
        const int rr = 16 * (wp & 3) + g + 8 * (i & 1);
        sy[i] = sbase + O_Y + (t * 584 + 64 * ((3 * wg + (i >> 1) + 63 - rr) % 9) + rr) * 4;
      }
      sts4(sbase + O_ST + tid * 16, movm(tb[0]), movm(tb[2]), movm(tb[1]), movm(tb[3]));
      sts4(sbase + O_ST + 6144 + tid * 16, sy[0], sy[1], sy[2], sy[3]);
      sts2(sbase + O_ST + 12288 + tid * 8, sy[4], sy[5]);
    }
  } else {
    __syncthreads();
  }

  const unsigned ep = upin(lds(full0 + 248));
  const uint32_t tag16 = tag_of(ep), tag1 = ep & 1;
  auto load_wm = [&](int u) {
    if (wp > 8 && elect()) {
      mbar_expect(full0 + 8 * B_WM, 6144);
      tma2d(sbase + O_NRM + (wp - 9) * 6144, &maps.wm, 16 * u, 192 * (wp - 9), full0 + 8 * B_WM);
    }
    __syncwarp();
  };
  if (R >= 0) {
    const int nl = (col0 + wp < DF_) + (wg < 2 && col0 + wp + 12 < DF_);
    uint4 cf[2][4], G[4];
#pragma unroll
    for (int i = 0; i < 4; i++) {
      cf[0][i] = __ldg(p.tab + TB_P2 + i * 32 + l);
      cf[1][i] = __ldg(p.tab + TB_P2 + (pi ? i : 4 + i) * 32 + l);
      G[i] = __ldg(p.tab + TB_P2 + (8 + i) * 32 + l);
    }
    const uint32_t* zin = sc->z1 + (size_t)R * 5120;
    if (wp == 10) {
      const uint32_t* zu = upin(zin);
      if (elect()) mbar_expect(full0 + 8 * B_Z1, 20480);
      wait_cnt(sc->cnt + C_Z1 + 32 * (pi >> 2), 128 * ep - 40 * STRESS);
      if (elect()) {
        bulk_ld(sbase + O_P2, zu, 20480, full0 + 8 * B_Z1);
        TS(12);
      }
      __syncwarp();
    }
    mbar_wait(full0 + 8 * B_FLT, 0);
    CK(9);
    float wn[16], wc[16];
#pragma unroll 1
    for (int ln = nl - 1; ln >= 0; ln--) {
      const int col = col0 + wp + 12 * ln, k2 = (57 * col) & 63;
      const bool cj = k2 > 32;
      const float nr = ((col & 31) == 0 && col != 0 && col != 288 ? 0.5f : 1.0f) / ((float)S_ * D_), ni = cj ? -nr : nr;
#pragma unroll
      for (int i = 0; i < 16; i++) wn[i] = wc[i];
#pragma unroll
      for (int cl = 0; cl < 2; cl++) {
        const int v = cl ^ (cj && pi), e = ((v ? xv : xu) & 15) + wp + 12 * ln, sh = e < 32 ? 6 : 5;
        const uint32_t base = sbase + O_RAW + v * 12288 + (e < 32 ? 2 * e : 8192 - 64 + 2 * e), msk = e < 32 ? 0x30 : 0x10;
        const int dm = v ? (cj || pi ? -1 : 0) : 0;
#pragma unroll
        for (int tt = 0; tt < 4; tt++) {
          const int kc = g + 64 * (tt >> 1) + 16 * t + 8 * (tt & 1);
          uint32_t a = base + ((((cj ? -kc : kc) + dm) & 127) << sh);
          a ^= (a >> 3) & msk;
          wc[4 * tt + 2 * cl] = lds_bf(a) * nr; wc[4 * tt + 2 * cl + 1] = lds_bf(a + 24576) * ni;
        }
      }
    }
    const float al = __uint_as_float(pin((pi ? 0x3f800000u : 0u) + (l >> 5)));
    const uint32_t tagv = pin(tag1 + (l >> 5));
    CK(10);
    uint32_t off = pin(l * 160 + ((wp ^ (g & 3)) << 3));
    uint32_t offo = pin(sbase + O_P2 + 20480 + off - 64 * l), po = 3072;
    unsigned* hz2 = pin(sc->cnt + C_Z2);
    const uint32_t do2 = pin(12288 - 32 * l);
    const CUtensorMap* mz2 = upin(&maps.z2[wp == 0]);
    const uint32_t sz2 = upin(sbase + O_P2 + 20480 + (wp ? 0 : 12288)), cz2 = upin(40 * R + (wp ? 0 : 24));
    mbar_wait(full0 + 8 * B_Z1, 0);
    CK(11);
    if (tid == 0) TS(8);
    if (wg == 2) load_wm(72 + mu);
    uint2 v[4], v2[4];
    const uint32_t o2 = nl > 1 ? 96 : 0;
#pragma unroll
    for (int i = 0; i < 4; i++) { v[i] = lds2(sbase + O_P2 + off + i * 5120); v2[i] = lds2(sbase + O_P2 + off + o2 + i * 5120); }
    auto bad2 = [&]() {
      return any(or3(or3(diff2(v[0].x, v[1].x, tagv), diff2(v[2].x, v[3].x, tagv), diff2(v2[0].x, v2[1].x, tagv)), diff2(v2[2].x, v2[3].x, tagv), 0) & 1);
    };
    if (__builtin_expect(bad2() && nl, 0)) {
      FAILCNT(0);
      int it = 0;
      do {
#pragma unroll
        for (int i = 0; i < 4; i++) {
          v[i] = ld_rlx2(reinterpret_cast<const uint8_t*>(zin) + off + i * 5120);
          v2[i] = ld_rlx2(reinterpret_cast<const uint8_t*>(zin) + off + o2 + i * 5120);
        }
      } while (bad2() && ++it < SPIN_MAX);
    }
#pragma unroll 1
    for (int ln = 0; ln < nl; ln++, offo += do2, po = 2048) {
      float d[4][4];
      uint32_t A[8];
#pragma unroll
      for (int h = 0; h < 2; h++) {
        mma16<false>(d[2 * h], cf[0][0].x, cf[0][0].y, cf[0][0].z, cf[0][0].w, v[h].x, v[2 + h].x);
        mma16<false>(d[2 * h + 1], cf[1][0].x, cf[1][0].y, cf[1][0].z, cf[1][0].w, v[h].y, v[2 + h].y);
      }
      if (ln) { fence_async_smem(); bar_arrive(15, NTHR); }
#pragma unroll
      for (int h = 0; h < 2; h++)
#pragma unroll
        for (int L = 0; L < 2; L++) {
          const uint4 tw = cf[L][2 + h];
          const float* z = d[2 * h + L];
          const float2 z0 = cmul(make_float2(z[0], z[2]), make_float2(__uint_as_float(tw.x), __uint_as_float(tw.y)));
          const float2 z1 = cmul(make_float2(z[1], z[3]), make_float2(__uint_as_float(tw.z), __uint_as_float(tw.w)));
          A[4 * h + L] = pack_bf16(z0.x, z0.y); A[4 * h + 2 + L] = pack_bf16(z1.x, z1.y);
        }
#pragma unroll
      for (int tt = 0; tt < 4; tt++) {
        mma16<false>(d[tt], A[0], A[1], A[2], A[3], G[tt].x, G[tt].y);
        mma16<true>(d[tt], A[4], A[5], A[6], A[7], G[tt].z, G[tt].w);
      }
#pragma unroll
      for (int tt = 0; tt < 4; tt++) {
        const float ar = d[tt][0], aj = d[tt][1], br = d[tt][2], bj = d[tt][3];
        const float2 y1 = cmul(make_float2(fmaf(-al, bj, ar), fmaf(al, br, aj)), make_float2(wc[4 * tt], wc[4 * tt + 1]));
        const float2 y2 = cmul(make_float2(fmaf(al, ar, bj), fmaf(al, aj, -br)), make_float2(wc[4 * tt + 2], wc[4 * tt + 3]));
        A[2 * tt] = pack_bf16(fmaf(al, y2.x, y1.x), fmaf(-al, y2.y, -y1.y));
        A[2 * tt + 1] = pack_bf16(fmaf(al, y1.y, -y2.y), fmaf(al, y1.x, -y2.x));
      }
#pragma unroll
      for (int i = 0; i < 16; i++) wc[i] = wn[i];
#pragma unroll
      for (int i = 0; i < 4; i++) v[i] = v2[i];
#pragma unroll
      for (int tt = 0; tt < 4; tt++) {
        mma16<false>(d[tt], A[0], A[1], A[2], A[3], G[tt].x, G[tt].y);
        mma16<true>(d[tt], A[4], A[5], A[6], A[7], G[tt].z, G[tt].w);
      }
#pragma unroll
      for (int h = 0; h < 2; h++)
#pragma unroll
        for (int L = 0; L < 2; L++) {
          const uint4 tw = cf[L][2 + h];
          const float2 z0 = cmul(make_float2(d[2 * h][2 * L], d[2 * h][2 * L + 1]), make_float2(__uint_as_float(tw.x), __uint_as_float(tw.y)));
          const float2 z1 = cmul(make_float2(d[2 * h + 1][2 * L], d[2 * h + 1][2 * L + 1]), make_float2(__uint_as_float(tw.z), __uint_as_float(tw.w)));
          A[4 * h + 2 * L] = movm(pack_bf16(z0.x, z1.x)); A[4 * h + 2 * L + 1] = movm(pack_bf16(z0.y, z1.y));
        }
#pragma unroll
      for (int h = 0; h < 2; h++) {
        mma16<false>(d[0], cf[0][1].x, cf[0][1].y, cf[0][1].z, cf[0][1].w, A[4 * h], A[4 * h + 1]);
        mma16<false>(d[1], cf[1][1].x, cf[1][1].y, cf[1][1].z, cf[1][1].w, A[4 * h + 2], A[4 * h + 3]);
#pragma unroll
        for (int e = 0; e < 2; e++)
          sts2(offo + (2 * h + e) * po, set_tag(pack_bf16(d[0][e], d[0][2 + e]), tagv), pack_bf16(d[1][e], d[1][2 + e]));
      }
      CK(12 + ln);
    }
    if (tid == 0) TS(1);
    fence_async_smem();
    if (nl < 2 && wp != 8) bar_arrive(15, NTHR);
    if (wp) bar_arrive(6, NTHR);
    if (!(wp & 7)) {
      bar_sync(wp ? 15 : 6, NTHR);
      if (elect()) tma_st2d(mz2, sz2, cz2, 0);
      if (wp == 0 && elect()) red_add(hz2, 1);
      if (tid == 0) TS(9);
      if (wp == 0) bulk_commit_wait();
      __syncwarp();
    }
  }
  if (wg == 2) {
#pragma unroll 1
    for (int u = 72 + mu, k = 0; u < 216; u += NCTA, k ^= 1) {
      if (R < 0) { fence_async_smem(); bar_sync(4, 128); load_wm(u); }
      mod_unit(sc, u, t128, sbase + O_NRM, full0 + 8 * B_WM, k, red + 256 - 256 * k, tag16);
    }
    fence_async_smem();
    CK(13);
  }

  const int grp = bx / 11, m1 = bx - 11 * grp;
  const bool helper = (m1 & 3) == 3;
  const int f1 = 384 * grp + (helper ? 192 : 128) * (m1 >> 2);
  const int d1 = 160 * (m1 & 3), flip = m1 >= 7;
  const int a1bytes = helper ? 24576 : 16384;
  auto load_a1 = [&](int st, int kb) {
    mbar_expect(full0 + 8 * st, a1bytes);
    tma4d_ef(sbase + st * STAGE, helper ? &maps.w1b : &maps.w1a, 4 * (kb >> 3), 16 * (kb & 7), f1 >> 6, full0 + 8 * st);
  };

  uint32_t bia[4];
  if (wg < 2) {
    const int fa = f1 + (helper ? 128 : 64) * (wg ^ flip) + 16 * (wp & 3) + g, fb = helper ? f1 + 64 + 16 * (wp & 3) + g : fa;
#pragma unroll
    for (int i = 0; i < 4; i++) asm volatile("ld.global.nc.u16 %0, [%1];" : "=r"(bia[i]) : "l"(p.b1 + (i < 2 ? fa : fb) + 8 * (i & 1)) : "memory");
  }
  if (rows) {
#pragma unroll
    for (int kk = 0; kk < 4; kk++) af[kk] = __ldg(p.tab + TB_E + kk * 128 + t128);
    const uint4 c0 = lds4(sbase + O_ST + tid * 16), c1 = lds4(sbase + O_ST + 6144 + tid * 16);
    const uint2 c2 = lds2(sbase + O_ST + 12288 + tid * 8);
    const uint32_t tc[4] = {c0.x, c0.y, c0.z, c0.w}, sy[6] = {c1.x, c1.y, c1.z, c1.w, c2.x, c2.y};
    const uint32_t l8 = pin(8 * l), syl = pin(sbase + O_Y + wp * 2336 + 8 * l);
    uint32_t sh3[3], ham[3];
#pragma unroll
    for (int k = 0; k < 3; k++) {
      const int pos = k && (l >> 4) == k - 1 ? 2 * (l & 6) + ((l >> 2) & 2) + (l & 1) : l & 15;
      const int sw = 2 * cta + ((wp >> 1) & 1), ph = pos ^ ((sw & 3) << 2);
      sh3[k] = pin((l >> 4) * 256 + (wp & 3) * 64 + ph * 4);
      ham[k] = pin(((ph ^ sw) & 7) == 0 ? ~1u : ~0u);
    }
    unsigned* const hh3 = upin(sc->cnt + C_H3 + (cta >> 4));
    uint8_t* const h3g = pin(sc->h3 + (cta >> 4) * (18 * 4096) + (cta & 15) * 256 + (l >> 4) * 3840);
    const int slot = 4 * (cta >> 4) + ((cta >> 1) & 3) + 32 * (2 * ((cta >> 3) & 1) + (cta & 1));
    const uint32_t* zin = sc->z2 + (size_t)slot * 4800;
    if (wg == 2) {
      {
        uint4 v[4];
        const int i3 = min(t128 + 384, 431);
        int it = 0;
        while (true) {
          uint32_t bad = 0;
#pragma unroll
          for (int k = 0; k < 4; k++) v[k] = ld_rlx4(sc->mod + 4 * (k < 3 ? t128 + 128 * k : i3));
#pragma unroll
          for (int k = 0; k < 4; k++) {
            v[k].x ^= tag16; v[k].y ^= tag16; v[k].z ^= tag16; v[k].w ^= tag16;
            bad |= v[k].x | v[k].y | v[k].z | v[k].w;
          }
          if (!any(bad & 0xffffu) || ++it > SPIN_MAX) break;
        }
#pragma unroll
        for (int k = 0; k < 4; k++) sts4(sbase + O_MOD + 16 * (k < 3 ? t128 + 128 * k : i3), v[k].x, v[k].y, v[k].z, v[k].w);
      }
      CK(14);
      bulk_commit_wait();
      bar_sync(10, NTHR);
      mbar_wait(full0 + 8 * B_Z2, 0);
      if (elect()) {
        load_a1(wp - 8, wp - 8);
      }
      __syncwarp();
    } else {
      const uint4 e0 = lds4(sbase + O_ST + 15360 + tid * 16), e1 = lds4(sbase + O_ST + 19456 + tid * 16), e2 = lds4(sbase + O_ST + 23552 + tid * 16);
      const uint32_t li[9] = {e0.x, e0.y, e0.z, e0.w, e1.x, e1.y, e1.z, e1.w, e2.x}, lx = e2.y, sb3 = e2.z;
      bar_arrive(10, NTHR);
      CK(14);
      if (wp == 1) {
        const uint32_t* zu = upin(zin);
        if (elect()) mbar_expect(full0 + 8 * B_Z2, 19200);
        wait_cnt(sc->cnt + C_Z2, 120 * ep - 40 * STRESS);
        if (elect()) {
          bulk_ld(sbase + O_IN, zu, 19200, full0 + 8 * B_Z2);
          TS(14);
        }
        __syncwarp();
      }
      mbar_wait(full0 + 8 * B_Z2, 0);
      CK(15);
      if (tid == 0) TS(11);
      uint2 v[10];
#pragma unroll
      for (int k1 = 0; k1 < 10; k1++) v[k1] = lds2(k1 < 9 ? li[k1] : lx);
      float2 za[9], zb[9];
      int it = 0;
#pragma unroll 1
      while (true) {
      const uint32_t bad = or3(or3(diff2(v[0].x, v[1].x, tag1), diff2(v[2].x, v[3].x, tag1), diff2(v[4].x, v[5].x, tag1)), diff2(v[6].x, v[7].x, tag1), diff2(v[8].x, v[9].x, tag1));
#pragma unroll
      for (int i = 0; i < 9; i++) { za[i] = make_float2(bf_lo(v[i].x), bf_hi(v[i].x)); zb[i] = make_float2(bf_lo(v[i].y), bf_hi(v[i].y)); }
      if ((wp & 3) == wg) {
        const float sp = g ? 0.f : 1.f;
#pragma unroll
        for (int k = 1; k < 5; k++) {
          float2 a = za[k], b = za[9 - k];
          za[k] = make_float2(fmaf(-sp, b.x, a.x), fmaf(sp, b.y, a.y)); za[9 - k] = make_float2(fmaf(sp, a.x, b.x), fmaf(-sp, a.y, b.y));
          a = zb[k]; b = zb[9 - k];
          zb[k] = make_float2(fmaf(-sp, b.x, a.x), fmaf(sp, b.y, a.y)); zb[9 - k] = make_float2(fmaf(sp, a.x, b.x), fmaf(-sp, a.y, b.y));
        }
        za[0].y = g ? za[0].y : bf_lo(v[9].x); zb[0].y = g ? zb[0].y : bf_lo(v[9].y);
      }
      dft9(za); dft9(zb);
#pragma unroll
      for (int n = 0; n < 8; n += 2) {
        const int i0 = (9 - n) % 9, i1 = 8 - n;
        stmatrix4(sb3 + n * 2048, pack_bf16(za[i0].x, zb[i0].x), pack_bf16(za[i0].y, zb[i0].y), pack_bf16(za[i1].x, zb[i1].x), pack_bf16(za[i1].y, zb[i1].y));
      }
      stmatrix2(sb3 + 8 * 2048, pack_bf16(za[1].x, zb[1].x), pack_bf16(za[1].y, zb[1].y));
      if (__builtin_expect(!any(bad & 1) || ++it > SPIN_MAX, 1)) break;
      FAILCNT(1);
#pragma unroll
      for (int k1 = 0; k1 < 10; k1++) v[k1] = ld_rlx2(reinterpret_cast<const uint8_t*>(zin) + (pin(k1 < 9 ? li[k1] : lx) - (sbase + O_IN)));
      }
      fence_async_smem();
    }
    CK(16);
    __syncthreads();
    CK(17);
    float acc[24];
    const uint32_t db = (((sbase + O_B3 + wg * 6144) & 0x3FFFF) >> 4) | ((128 >> 4) << 16);
    wg_fence();
#pragma unroll
    for (int kk = 0; kk < 4; kk++) wgmma_rs_48(acc, af[kk].x, af[kk].y, af[kk].z, af[kk].w, db + kk * 16, 1024 >> 4, kk);
    wg_commit();
    uint32_t ga[9];
    if (wg < 2) {
#pragma unroll
      for (int i = 0; i < 9; i++) { const uint2 v = lds2(l8 + sbase + O_MOD + 256 * i); ga[i] = __byte_perm(v.x, v.y, 0x7632); }
    }
    wg_wait<0>();
    reg_fence(acc);
    CK(18);
#pragma unroll
    for (int i = 0; i < 3; i++) {
      const float* a = &acc[8 * i];
      const uint32_t a0 = pack_bf16(a[0], a[1]), a1 = pack_bf16(a[2], a[3]), a2 = pack_bf16(a[4], a[5]), a3 = pack_bf16(a[6], a[7]);
#pragma unroll
      for (int jh = 0; jh < 2; jh++) {
        float y[4];
        mma16<false>(y, a0, a1, a2, a3, tc[2 * jh], tc[2 * jh + 1]);
        sts(sy[2 * i] + jh * (4 * 584 * 4), pack_bf16(y[0], y[1]));
        sts(sy[2 * i + 1] + jh * (4 * 584 * 4), pack_bf16(y[2], y[3]));
      }
    }
    CK(19);
    if (wg == 2) bar_arrive(7, NTHR); else bar_sync(7, NTHR);
    if (wg) bar_sync(15, NTHR);
    if (wg < 2) {
      CK(20);
      uint2 y[9], sh[9], sw[9];
#pragma unroll
      for (int i = 0; i < 9; i++) y[i] = lds2(syl + 256 * i);
      uint32_t sel = 0x5410, sto = sbase + O_B3 + wg * 9216;
#pragma unroll 1
      for (int e = 0; e < 2; e++, sel = 0x7632, sto += 4608) {
        float a[18];
#pragma unroll
        for (int i = 0; i < 9; i++) {
          const uint32_t x1 = hfma2(ga[i], __byte_perm(y[i].x, y[i].y, sel), xr[i]);
          xr[i] = xr[9 + i]; xr[9 + i] = x1;
          a[2 * i] = bf_lo(x1); a[2 * i + 1] = bf_hi(x1);
        }
#pragma unroll
        for (int i = 0; i < 9; i++) { lds2_if(!e, sh[i], l8 + sbase + O_MOD + 4 * D_ + 256 * i); lds2_if(!e, sw[i], l8 + sbase + O_MOD + 8 * D_ + 256 * i); }
        float oa, ra;
        ln_stats1(a, 1.0f, oa, ra);
#pragma unroll
        for (int i = 0; i < 9; i++) {
          a[2 * i] = fmaf(fmaf(a[2 * i], ra, oa), __uint_as_float(sw[i].x), __uint_as_float(sh[i].x));
          a[2 * i + 1] = fmaf(fmaf(a[2 * i + 1], ra, oa), __uint_as_float(sw[i].y), __uint_as_float(sh[i].y));
        }
        ln_stats1(a, 0.5f, oa, ra);
        uint32_t hv[9];
#pragma unroll
        for (int i = 0; i < 9; i++) hv[i] = bitsel(pack_bf16(fmaf(a[2 * i], ra, oa), fmaf(a[2 * i + 1], ra, oa)), ham[i == 2 ? 1 : i == 6 ? 2 : 0], tag1);
        if (!(wg | e)) {
          if (elect()) red_add(hh3, 1);
#pragma unroll
          for (int i = 0; i < 9; i++) asm volatile("st.global.b32 [%0], %1;" ::"l"(h3g + sh3[i == 2 ? 1 : i == 6 ? 2 : 0] + i * 8192), "r"(hv[i]) : "memory");
          bar_arrive(15, NTHR);
          if (tid == 0) TS(13);
        } else {
#pragma unroll
          for (int i = 0; i < 9; i++) sts(sto + sh3[i == 2 ? 1 : i == 6 ? 2 : 0] + i * 512, hv[i]);
        }
        if (!e) bar_arrive(8, 288);
        CK(21 + e);
      }
      fence_async_smem();
      bar_arrive(9, 288);
      CK(23);
    }
  }

  const bool g2 = rows;
  const int z2 = cta, r = z2 >> 6;
  const int s2 = 128 * ((z2 >> 2) & 15), d2 = 144 * (z2 & 3);
  constexpr int ST0 = 32 % NST;
  const bool first = helper || m1 < W0N;

  if (wg == 2) {
    asm volatile("setmaxnreg.dec.sync.aligned.u32 40;");
    auto load_b = [&](bool second, int i, int st) {
      const uint32_t lb = full0 + 8 * (B_LAND + st), bytes = second ? 18432 : STAGE - a1bytes;
      mbar_expect(lb, bytes);
      bulk_ld(sbase + (second ? st * STAGE2 + 16384 : st * STAGE + a1bytes),
              second ? sc->u + ((size_t)(36 * r + kb2_order(i)) * D_ + d2) * 128 : sc->h3 + ((size_t)(i * 18 + (d1 >> 5)) << 12), bytes, lb);
    };
    if (wp == 8) {
      int st = rows ? 4 : 0, ph = 1;
#pragma unroll 1
      for (int kb = st; kb < 32; kb++) {
        if (rows && (kb >> 1) == 2) mbar_wait(full0 + 8 * (B_S4 - 4 + kb), 0);
        mbar_wait(empty0 + 8 * st, ph);
        if (elect()) {
          load_a1(st, kb);
        }
        __syncwarp();
        ring_next<false>(st, ph);
      }
      if (g2) {
        st++;
#pragma unroll 1
        for (int i = 0; i < 36; i++) {
          if (i == HOLDA) mbar_wait(full0 + 8 * B_GO, 0);
          mbar_wait(empty0 + 8 * st, ph);
          if (elect()) {
            mbar_expect(full0 + 8 * st, 16384);
            tma3d_ef(sbase + st * STAGE2, &maps.w2, 64 * (36 * r + kb2_order(i)), s2 >> 6, full0 + 8 * st);
          }
          __syncwarp();
          ring_next<true>(st, ph);
        }
      }
    } else if (wp >= 10) {
      const int sw = wp - 10;
      if (sw) {
        if (rows) {
          bar_sync(8, 288);
          mbar_wait(full0 + 8 * H3W, 0);
          if (elect()) mbar_arrive(full0 + 8 * B_S4);
          bar_sync(9, 288);
          if (elect()) tma_st3d(&maps.h3, sbase + O_B3 + 4608, 64 * (cta & 15), 18 * (cta >> 4), 1);
          bulk_commit_wait();
          if (elect()) {
            red_add(sc->cnt + C_H3 + (cta >> 4) + 8, 4);
            mbar_arrive(full0 + 8 * B_S5);
            TS(24);
            asm volatile("fence.acq_rel.gpu;" ::: "memory");
            red_add(&sc->cnt[C_X + 64], 1);
          }
          __syncwarp();
        }
        if (g2) {
          uint2 v[3];
          int it = 0;
          do {
#pragma unroll
            for (int i = 0; i < 3; i++) v[i] = ld_rlx2(sc->mod + 3 * D_ + d2 + 2 * min(l + 32 * i, 71));
          } while (any(or3(diff2(v[0].x, v[0].y, tag16), diff2(v[1].x, v[1].y, tag16), diff2(v[2].x, v[2].y, tag16)) & 0xffffu) && ++it < SPIN_MAX);
#pragma unroll
          for (int i = 0; i < 3; i++) sts(sbase + O_GB + 4 * min(l + 32 * i, 71), __byte_perm(v[i].x, v[i].y, 0x7632));
          __syncwarp();
        }
        wait_cnt<true>(&sc->cnt[C_X + 64], 128 * ep);
        if (elect()) mbar_arrive(full0 + 8 * B_X);
        __syncwarp();
      }
      uint32_t lph = 0;
      auto check_tiles = [&](bool second, int n, int st, uint32_t o1, uint32_t d2nd) {
        const uint32_t b1 = pin(sbase + o1), b2 = pin(sbase + o1 + d2nd);
        int i = 0, it = 0;
#pragma unroll 1
        do {
          const uint32_t so = st * (second ? STAGE2 : STAGE);
          mbar_wait(full0 + 8 * (B_LAND + st), (lph >> st) & 1);
          lph ^= 1u << st;
          uint32_t v[20];
#pragma unroll
          for (int k = 0; k < 20; k++) if (!second || k < 10 || k >= 12) v[k] = lds(k < 12 ? b1 + so + k * 1024 : b2 + so + (k - 12) * 1024); else v[k] = tag1;
#pragma unroll
          for (int k = 0; k < 10; k++) v[k] = diff2(v[2 * k], v[2 * k + 1], tag1);
          const uint32_t bad = or3(or3(or3(v[0], v[1], v[2]), or3(v[3], v[4], v[5]), v[6]), v[7], or3(v[8], v[9], 0));
          if (__builtin_expect(any(bad & 1) && ++it < SPIN_MAX, 0)) {
            FAILCNT(2 + second);
            fence_async_smem();
            __syncwarp();
            if (elect()) load_b(second, i, st);
            __syncwarp();
            continue;
          }
          if (elect()) mbar_arrive(full0 + 8 * st);
          if (++st == NST) st = 0;
          i++;
        } while (i < n);
      };
      if (!sw) check_tiles(false, NV1, 0, a1bytes + l * 32 + (l >> 2) * 4, helper ? 4096 : 12288);
      if (sw) {
#pragma unroll 1
        for (int k = 0; k < 2; k++) {
          bar_sync(13 + k, 160);
          if (helper || (first && !k)) continue;
          const uint32_t stg = sbase + (k ? O_U1 : ST0 * STAGE);
          const int kb = (f1 >> 6) + (k ^ flip);
          uint8_t* const ug = sc->u + ((size_t)kb * D_ + d1) * 128;
          if (g2) mbar_wait(full0 + 8 * B_GO, 0);
          if (first) pause(10 * TRK0);
#pragma unroll 1
          for (int i = 0; i < 20480; i += 2048) {
            if (elect()) bulk_st(ug + i, stg + i, 2048);
            pause(k ? TRKC : TRK0);
          }
          if (elect()) red_add(sc->cnt + C_U + kb2_pos(kb), 4);
          bulk_commit_wait();
          if (elect()) { if (!k) mbar_arrive(empty0 + 8 * ST0); TS(k ? 23 : 17); }
          __syncwarp();
        }
        if (elect()) { asm volatile("fence.acq_rel.gpu;" ::: "memory"); red_add(&sc->cnt[C_X], 1); }
        __syncwarp();
      }
      if (g2) {
        if (!sw) check_tiles(true, NV2, 3, 16384 + l * 32 + g * 4, 10240);
        else {
          wait_cnt<true>(&sc->cnt[C_X], NCTA * ep);
          if (elect()) mbar_arrive(full0 + 8 * B_X);
          if (cta == 0) sc->cnt[C_EP + (pin(l) ^ 1)] = ep;
          __syncwarp();
        }
      }
      __syncwarp();
    } else {
      uint32_t ready = 0;
      int st = 0, ph = 1;
#pragma unroll 1
      for (int kb = 0; kb < 32; kb++) {
        const uint8_t* src = upin(sc->h3 + ((size_t)(kb * 18 + (d1 >> 5)) << 12));
        const uint32_t dst = upin(sbase + st * STAGE + a1bytes), lb = full0 + 8 * ((kb < NV1 ? B_LAND : 0) + st);
        if (kb == NV1) { mbar_wait(full0 + 8 * B_X, 0); fence_async_glb(); ready = ~0u; }
        if (rows && (kb >> 1) == 2) mbar_wait(full0 + 8 * (B_S4 - 4 + kb), 0);
        mbar_wait(empty0 + 8 * st, ph);
        if (elect()) mbar_expect(lb, STAGE - a1bytes);
        wait_flags(sc->cnt + C_H3 + l, (kb & 7) + (kb < 8 ? 0 : 8), 64 * ep - 24 * STRESS, ready);
        if (elect()) bulk_ld(dst, src, STAGE - a1bytes, lb);
        ring_next<false>(st, ph);
      }
      if (g2) {
        ready = 0;
        st++;
#pragma unroll 1
        for (int i = 0; i < 36; i++) {
          const int kb = kb2_order(i);
          const uint8_t* src = upin(sc->u + ((size_t)(36 * r + kb) * D_ + d2) * 128);
          const uint32_t dst = upin(sbase + st * STAGE2 + 16384), lb = full0 + 8 * ((i < NV2 ? B_LAND : 0) + st);
          if (i == NV2) { mbar_wait(full0 + 8 * B_X, 1); fence_async_glb(); ready = ~0u; }
          mbar_wait(empty0 + 8 * st, ph);
          if (elect()) mbar_expect(lb, 18432);
          wait_flags(sc->cnt + C_U + 64 * r + l, i & 31, 16 * ep - 8 * STRESS, ready);
          if (elect()) {
            bulk_ld(dst, src, 18432, lb);
            if (i == GOAT) mbar_arrive(full0 + 8 * B_GO);
          }
          ring_next<true>(st, ph);
        }
      }
    }
  } else {
    asm volatile("setmaxnreg.inc.sync.aligned.u32 232;");
    const int wgu = wg;
    constexpr uint32_t sb4 = sbase >> 4;
    const int w = wp & 3;
    Ring rg = {0, 0};
    uint32_t* const x1p = p.out + (size_t)(cta + 128 * ((wp & 3) + 8 * wg)) * 288 + l;
    const int direct = helper || (first && !wg), kbA = (f1 >> 6) + (helper ? 2 : 1) * (wg ^ flip), kbB = (f1 >> 6) + 1;
    const uint32_t uo = (t >> 1) * 2048 + (16 * w + g) * 32 + (((t ^ (g >> 2)) & 1) << 4);
    const uint32_t ad = pin(sbase + (wg ? O_U1 : ST0 * STAGE) + uo);
    uint8_t* const ug0 = pin(sc->u + ((size_t)kbA * D_ + d1) * 128 + uo);
    const int ud1 = upin(helper ? (kbB - kbA) * (D_ * 128) - 3 * 4096 : 0);
    unsigned* const uh = pin(sc->cnt + C_U + kb2_pos(l ? kbB : kbA));
    const int eh = direct && !helper && !l;
    const bool utg = ((t ^ (g >> 2) ^ w) & 1) == 0;
    const uint32_t um0 = pin(utg && g < 4 ? ~1u : ~0u), um1 = pin(utg && g >= 4 ? ~1u : ~0u);
    float acc[96];
    constexpr uint32_t LA = (8192 >> 4) << 16, LB = (4096 >> 4) << 16;
    {
      const float a0 = 0.5f * bf_lo(pin(bia[0])), a1 = 0.5f * bf_lo(pin(bia[1])), b0 = 0.5f * bf_lo(pin(bia[2])), b1 = 0.5f * bf_lo(pin(bia[3]));
#pragma unroll
      for (int i = 0; i < 96; i++) acc[i] = i < 48 ? ((i & 2) ? a1 : a0) : ((i & 2) ? b1 : b0);
      reg_fence(acc);
    }
    if (!helper) gemm_main<0>(acc, sb4 + (wgu ^ flip) * 512 + LA, 0, sb4 + 1024 + LB, wgu, rg, rows, first ? NST : NST - 1, x1p, xr);
    else {
      float ac2[96];
#pragma unroll
      for (int i = 0; i < 96; i++) asm volatile("mov.b32 %0, %1;" : "=f"(ac2[i]) : "f"(acc[i]));
      gemm_main<1>(ac2, sb4 + (wgu ^ flip) * 1024 + LA, sb4 + 512 + LA, sb4 + 1536 + LB, wgu, rg, rows, NST - 1, x1p, xr);
#pragma unroll
      for (int i = 0; i < 96; i++) asm volatile("mov.b32 %0, %1;" : "=f"(acc[i]) : "f"(ac2[i]));
    }
    if (t128 == 0) { TS(wg ? 16 : 6); if (wg) TSC(5); }
    {
      float tp[2] = {0.f, 0.f};
#pragma unroll
      for (int j = 0; j < 12; j++) {
        const float* a = &acc[16 * (j >> 1) + 2 * (j & 1)];
        const float k3 = j < 2 ? (GV ? GK1 : GK3) : fmaf(tp[j & 1], 0.0f, GV ? GK1 : GK3);
        uint32_t o[4];
#pragma unroll
        for (int e = 0; e < 4; e++) {
          const float h0 = a[4 * e], h1 = a[4 * e + 1];
          float z0 = GV ? h0 * fmaf(h0 * h0, GK3, k3) : h0 * fmaf(h0 * k3, h0, GK1), z1 = GV ? h1 * fmaf(h1 * h1, GK3, k3) : h1 * fmaf(h1 * k3, h1, GK1);
          asm("tanh.approx.f32 %0, %0;" : "+f"(z0));
          asm("tanh.approx.f32 %0, %0;" : "+f"(z1));
          if (e == GDEP) tp[j & 1] = z0;
          o[e] = pack_bf16(fmaf(h0, z0, h0), fmaf(h1, z1, h1));
          if ((e >> 1) == (j & 1)) o[e] = bitsel(o[e], (e & 1) ? um1 : um0, tag1);
        }
        if (EH && j == EH) asm volatile("{\n.reg .pred p;\nsetp.ne.u32 p, %1, 0;\n@p red.relaxed.gpu.global.add.u32 [%0], 1;\n}" ::"l"(uh), "r"(eh) : "memory");
        asm volatile("{\n.reg .pred p;\nsetp.ne.u32 p, %6, 0;\n@p st.global.v4.b32 [%0], {%2,%3,%4,%5};\n@!p st.shared.v4.b32 [%1], {%2,%3,%4,%5};\n}"
                     ::"l"(ug0 + (j < 6 ? 0 : ud1) + (j >> 1) * 4096 + (j & 1) * 256), "r"(ad + (j >> 1) * 4096 + (j & 1) * 256),
                       "r"(o[0]), "r"(o[1]), "r"(o[2]), "r"(o[3]), "r"(direct) : "memory");
        if ((j == 5 && helper && !wgu) || (j == 9 && !helper)) break;
      }
      if (!direct) fence_async_smem();
      else if (l <= wgu && (EH == 0 || helper)) red_add(uh, 1);
      __syncwarp();
      bar_arrive(13 + wgu, 160);
      if (t128 == 0) TS(wg ? 29 : 28);
    }
    if (g2) {
      const int mb = wgu ^ r;
      const int odd = z2 & 1;
      uint4 gq[4];
      uint2 gs;
      {
        float a0 = 0.f, a1 = 0.f;
        if (wgu) { a0 = __bfloat162float(p.b2[s2 + 64 * mb + 16 * w + g]); a1 = __bfloat162float(p.b2[s2 + 64 * mb + 16 * w + 8 + g]); }
#pragma unroll
        for (int i = 0; i < 4; i++) gq[i] = lds4(sbase + O_GB + 32 * odd + 64 * i + 16 * t);
        gs = lds2(sbase + O_GB + (odd ? 0 : 256) + 8 * t);
#pragma unroll
        for (int i = 0; i < 72; i++) acc[i] = (i & 2) ? a1 : a0;
      }
      uint32_t* const ob = p.out + (size_t)(s2 + 64 * mb + 16 * w + g) * 288 + (d2 >> 1);
      uint32_t* const oq = pin(ob + 8 * odd + 4 * t);
      uint32_t* const os = pin(ob + (odd ? 0 : 64) + 2 * t);
      rg.st++;
      gemm_main<3>(acc, sb4 + mb * 512 + LA, 0, sb4 + 1024 + ((2048 >> 4) << 16), wgu, rg, rows, NST, x1p, xr);
      if (t128 == 0) { TS(wg ? 20 : 19); if (wg) TSC(22); }
      auto finish = [&](const float* aq, const float* as) {
#pragma unroll
        for (int i = 0; i < 8; i++) {
          const float* a = aq + 16 * (i >> 1) + 2 * (i & 1);
          const uint4 gv = gq[i >> 1];
          red_bf16x8(oq + (i & 1) * 2304 + 16 * (i >> 1), hmul2(gv.x, pack_bf16(a[0], a[1])), hmul2(gv.y, pack_bf16(a[4], a[5])),
                     hmul2(gv.z, pack_bf16(a[8], a[9])), hmul2(gv.w, pack_bf16(a[12], a[13])));
        }
#pragma unroll
        for (int i = 0; i < 2; i++) red_bf16x4(os + i * 2304, hmul2(gs.x, pack_bf16(as[2 * i], as[2 * i + 1])), hmul2(gs.y, pack_bf16(as[2 * i + 4], as[2 * i + 5])));
      };
      if (odd) finish(&acc[8], &acc[0]); else finish(&acc[0], &acc[64]);
      if (t128 == 0) TS(wg ? 7 : 21);
      __syncwarp();
    }
  }
}

typedef CUresult (*EncodeFn)(CUtensorMap*, CUtensorMapDataType, cuuint32_t, void*, const cuuint64_t*, const cuuint64_t*, const cuuint32_t*,
                             const cuuint32_t*, CUtensorMapInterleave, CUtensorMapSwizzle, CUtensorMapL2promotion, CUtensorMapFloatOOBfill);

struct Dim { cuuint64_t n, stride; cuuint32_t box; };
template <int RANK>
void make_map(EncodeFn enc, CUtensorMap* m, bool words, int swz, const void* ptr, const Dim (&d)[RANK]) {
  cuuint64_t gd[RANK], gs[RANK];
  cuuint32_t bx[RANK], es[RANK];
  for (int i = 0; i < RANK; i++) { gd[i] = d[i].n; gs[i] = d[i].stride; bx[i] = d[i].box; es[i] = 1; }
  enc(m, words ? CU_TENSOR_MAP_DATA_TYPE_UINT32 : CU_TENSOR_MAP_DATA_TYPE_BFLOAT16, RANK, const_cast<void*>(ptr), gd, gs + 1, bx, es,
      CU_TENSOR_MAP_INTERLEAVE_NONE, static_cast<CUtensorMapSwizzle>(swz),
      swz == 3 ? CU_TENSOR_MAP_L2_PROMOTION_L2_256B : CU_TENSOR_MAP_L2_PROMOTION_NONE, CU_TENSOR_MAP_FLOAT_OOB_FILL_NONE);
}

}

extern "C" void kernel_launch(void* const* d_in, const int* in_sizes, int n_in, void* d_out, int out_size) {
  (void)in_sizes; (void)n_in; (void)out_size;
  static EncodeFn enc = nullptr;
  static void *sptr = nullptr, *tptr = nullptr;
  if (!enc) {
    void* f = nullptr; cudaDriverEntryPointQueryResult qr;
    cudaGetDriverEntryPoint("cuTensorMapEncodeTiled", &f, cudaEnableDefault, &qr);
    enc = reinterpret_cast<EncodeFn>(f);
    cudaFuncSetAttribute(fused_kernel, cudaFuncAttributeMaxDynamicSharedMemorySize, SMEM_BYTES);
    cudaGetSymbolAddress(&sptr, g_s);
    cudaGetSymbolAddress(&tptr, T_TAB);
  }
  Params p;
  p.x = (const __nv_bfloat16*)d_in[0]; p.wr = (const __nv_bfloat16*)d_in[1]; p.wi = (const __nv_bfloat16*)d_in[2];
  p.b1 = (const __nv_bfloat16*)d_in[5]; p.b2 = (const __nv_bfloat16*)d_in[7];
  p.c = (const __nv_bfloat16*)d_in[8]; p.wmod = (const __nv_bfloat16*)d_in[9];
  p.w1 = (const __nv_bfloat16*)d_in[4]; p.w2 = (const __nv_bfloat16*)d_in[6];
  p.out = static_cast<uint32_t*>(d_out); p.s = static_cast<Scratch*>(sptr); p.tab = static_cast<const uint4*>(tptr);
  Maps maps;
  make_map<4>(enc, &maps.w1a, false, 3, p.w1, {{64, 0, 64}, {16, 128 * 2 * F_, 4}, {128, 2 * F_, 16}, {72, 128, 2}});
  make_map<4>(enc, &maps.w1b, false, 3, p.w1, {{64, 0, 64}, {16, 128 * 2 * F_, 4}, {128, 2 * F_, 16}, {72, 128, 3}});
  make_map<3>(enc, &maps.w2, false, 3, p.w2, {{64, 0, 64}, {F_, 2 * S_, 64}, {32, 128, 2}});
  make_map<2>(enc, &maps.z1, true, 0, p.s->z1, {{5120, 0, 40}, {120, 20480, 60}});
  for (int i = 0; i < 2; i++) make_map<2>(enc, &maps.z2[i], true, 0, p.s->z2, {{4800, 0, i ? 16u : 24u}, {128, 19200, 128}});
  for (int i = 0; i < 4; i++) make_map<2>(enc, &maps.wf[i], false, 2 - (i & 1), (i & 2) ? p.wi : p.wr, {{16 * DF_, 0, (i & 1) ? 16u : 32u}, {128, 32 * DF_, 128}});
  make_map<2>(enc, &maps.wm, false, 1, p.wmod, {{6 * D_, 0, 16}, {D_, 12 * D_, 192}});
  make_map<3>(enc, &maps.h3, true, 0, p.s->h3, {{1024, 0, 64}, {144, 4096, 18}, {4, 144 * 4096, 3}});
  fused_kernel<<<NCTA, NTHR, SMEM_BYTES, cudaStreamPerThread>>>(p, maps);
}
```

```cpp
#include <cuda_runtime.h>
#include <cuda_bf16.h>
#include <cuda.h>
#include <stdint.h>

namespace {

constexpr int S_ = 2048, D_ = 576, DF_ = 289, F_ = 4608;
constexpr int NCTA = 132, NTHR = 384;
constexpr int STAGE = 36864, NST = 6;
constexpr int STAGE2 = 34816, O_U1 = NST * STAGE2, O_GB = O_U1 + 20480, SMEM_BYTES = 232448;
constexpr uint32_t sbase = 1024, red = sbase + NST * STAGE, full0 = sbase + SMEM_BYTES - 256, empty0 = full0 + 8 * NST;
constexpr int O_NRM = 0, O_B1 = 19456, O_Z1 = 38912, O_P2 = 59392, O_ST = 3 * STAGE;
constexpr int O_RAW = 4 * STAGE;
constexpr int O_IN = 4 * STAGE, O_Y = O_IN + 19456, O_B3 = O_IN + 38912, O_MOD = O_IN + 57344;

__device__ __align__(128) const uint32_t T_TAB[5632] = {
0x3f803f80,0xbf803f80,0x3f803f80,0xbf803f80,0x3f803f80,0xbf803f80,0x3f803f80,0xbf803f80,0x3f803f80,0xbf803f80,0x3f803f80,0xbf803f80,
0x3f803f80,0xbf803f80,0x3f803f80,0xbf803f80,0x3f7f3f80,0xbdc90000,0x3f223f35,0xbf46bf35,0x3f753f7b,0xbe95be48,0x3ef13f0e,0xbf62bf55,
0x3f623f6d,0xbef1bec4,0x3e953ec4,0xbf75bf6d,0x3f463f55,0xbf22bf0e,0x3dc93e48,0xbf7fbf7b,0x3f7b3f80,0xbe480000,0xbe480000,0xbf7bbf80,
0x3f553f6d,0xbf0ebec4,0xbf0ebec4,0xbf55bf6d,0x3f0e3f35,0xbf55bf35,0xbf55bf35,0xbf0ebf35,0x3e483ec4,0xbf7bbf6d,0xbf7bbf6d,0xbe48bec4,
0x3f753f80,0xbe950000,0xbf62bf35,0xbef1bf35,0x3f223f55,0xbf46bf0e,0xbf7fbf7b,0x3dc9be48,0x3dc93ec4,0xbf7fbf6d,0xbf46bf6d,0x3f223ec4,
0xbef1be48,0xbf62bf7b,0xbe95bf0e,0x3f753f55,0x3f6d3f80,0xbec40000,0xbf6dbf80,0x3ec40000,0x3ec43f35,0xbf6dbf35,0xbec4bf35,0x3f6d3f35,
0xbec40000,0xbf6dbf80,0x3ec40000,0x3f6d3f80,0xbf6dbf35,0xbec4bf35,0x3f6d3f35,0x3ec43f35,0x3f623f80,0xbef10000,0xbe95bf35,0x3f753f35,
0x3dc93f0e,0xbf7fbf55,0x3f223e48,0x3f463f7b,0xbf46bec4,0xbf22bf6d,0x3f7f3f6d,0xbdc93ec4,0xbf75bf7b,0x3e95be48,0x3ef13f55,0xbf62bf0e,
0x3f553f80,0xbf0e0000,0x3f0e0000,0x3f553f80,0xbe483ec4,0xbf7bbf6d,0x3f7b3f6d,0xbe483ec4,0xbf7bbf35,0xbe48bf35,0x3e483f35,0xbf7bbf35,
0xbf0ebf6d,0x3f553ec4,0xbf55bec4,0xbf0ebf6d,0x3f463f80,0xbf220000,0x3f7f3f35,0x3dc93f35,0xbef13e48,0xbf62bf7b,0x3e953f55,0xbf75bf0e,
0xbf75bf6d,0x3e95bec4,0xbf62bec4,0xbef1bf6d,0x3dc9bf0e,0x3f7f3f55,0xbf22bf7b,0x3f463e48,0x3f353f80,0xbf350000,0x3f353f80,0xbf350000,
0xbf350000,0xbf35bf80,0xbf350000,0xbf35bf80,0xbf35bf80,0x3f350000,0xbf35bf80,0x3f350000,0x3f350000,0x3f353f80,0x3f350000,0x3f353f80,
0x3f223f80,0xbf460000,0xbdc93f35,0xbf7fbf35,0xbf62be48,0xbef1bf7b,0xbf75bf55,0x3e95bf0e,0xbe95bf6d,0x3f753ec4,0x3ef1bec4,0x3f623f6d,
0x3f7f3f0e,0x3dc93f55,0x3f463f7b,0xbf223e48,0x3f0e3f80,0xbf550000,0xbf550000,0xbf0ebf80,0xbf7bbec4,0xbe48bf6d,0xbe48bf6d,0x3f7b3ec4,
0x3e48bf35,0x3f7b3f35,0x3f7b3f35,0xbe483f35,0x3f553f6d,0xbf0e3ec4,0xbf0e3ec4,0xbf55bf6d,0x3ef13f80,0xbf620000,0xbf75bf35,0x3e95bf35,
0xbf7fbf0e,0x3dc9bf55,0x3f46be48,0x3f223f7b,0x3f22bec4,0x3f463f6d,0x3dc93f6d,0xbf7fbec4,0x3e953f7b,0xbf75be48,0xbf62bf55,0x3ef1bf0e,
0x3ec43f80,0xbf6d0000,0xbec4bf80,0x3f6d0000,0xbf6dbf35,0x3ec4bf35,0x3f6d3f35,0xbec43f35,0x3f6d0000,0x3ec43f80,0xbf6d0000,0xbec4bf80,
0xbec43f35,0xbf6dbf35,0x3ec4bf35,0x3f6d3f35,0x3e953f80,0xbf750000,0x3ef1bf35,0x3f623f35,0xbf46bf55,0x3f22bf0e,0x3dc93f7b,0xbf7fbe48,
0x3f7f3ec4,0xbdc93f6d,0xbf22bf6d,0x3f46bec4,0xbf623e48,0xbef1bf7b,0x3f753f0e,0xbe953f55,0x3e483f80,0xbf7b0000,0x3f7b0000,0x3e483f80,
0xbf0ebf6d,0x3f55bec4,0xbf553ec4,0xbf0ebf6d,0x3f553f35,0xbf0e3f35,0x3f0ebf35,0x3f553f35,0xbf7bbec4,0x3e48bf6d,0xbe483f6d,0xbf7bbec4,
0x3dc93f80,0xbf7f0000,0x3f463f35,0xbf223f35,0xbe95bf7b,0x3f75be48,0xbf62bf0e,0x3ef1bf55,0x3ef13f6d,0xbf623ec4,0x3f753ec4,0xbe953f6d,
0xbf22bf55,0x3f46bf0e,0xbf7fbe48,0x3dc9bf7b,0x3f80,0xbf800000,0x3f80,0xbf800000,0xbf80,0x3f800000,0xbf80,0x3f800000,
0x3f80,0xbf800000,0x3f80,0xbf800000,0xbf80,0x3f800000,0xbf80,0x3f800000,0xbdc93f80,0xbf7f0000,0xbf463f35,0xbf22bf35,
0x3e95bf7b,0x3f753e48,0x3f62bf0e,0x3ef13f55,0xbef13f6d,0xbf62bec4,0xbf753ec4,0xbe95bf6d,0x3f22bf55,0x3f463f0e,0x3f7fbe48,0x3dc93f7b,
0xbe483f80,0xbf7b0000,0xbf7b0000,0x3e48bf80,0x3f0ebf6d,0x3f553ec4,0x3f553ec4,0xbf0e3f6d,0xbf553f35,0xbf0ebf35,0xbf0ebf35,0x3f55bf35,
0x3f7bbec4,0x3e483f6d,0x3e483f6d,0xbf7b3ec4,0xbe953f80,0xbf750000,0xbef1bf35,0x3f62bf35,0x3f46bf55,0x3f223f0e,0xbdc93f7b,0xbf7f3e48,
0xbf7f3ec4,0xbdc9bf6d,0x3f22bf6d,0x3f463ec4,0x3f623e48,0xbef13f7b,0xbf753f0e,0xbe95bf55,0xbec43f80,0xbf6d0000,0x3ec4bf80,0x3f6d0000,
0x3f6dbf35,0x3ec43f35,0xbf6d3f35,0xbec4bf35,0xbf6d0000,0x3ec4bf80,0x3f6d0000,0xbec43f80,0x3ec43f35,0xbf6d3f35,0xbec4bf35,0x3f6dbf35,
0xbef13f80,0xbf620000,0x3f75bf35,0x3e953f35,0x3f7fbf0e,0x3dc93f55,0xbf46be48,0x3f22bf7b,0xbf22bec4,0x3f46bf6d,0xbdc93f6d,0xbf7f3ec4,
0xbe953f7b,0xbf753e48,0x3f62bf55,0x3ef13f0e,0xbf0e3f80,0xbf550000,0x3f550000,0xbf0e3f80,0x3f7bbec4,0xbe483f6d,0x3e48bf6d,0x3f7bbec4,
0xbe48bf35,0x3f7bbf35,0xbf7b3f35,0xbe48bf35,0xbf553f6d,0xbf0ebec4,0x3f0e3ec4,0xbf553f6d,0xbf223f80,0xbf460000,0x3dc93f35,0xbf7f3f35,
0x3f62be48,0xbef13f7b,0x3f75bf55,0x3e953f0e,0x3e95bf6d,0x3f75bec4,0xbef1bec4,0x3f62bf6d,0xbf7f3f0e,0x3dc9bf55,0xbf463f7b,0xbf22be48,
0xbf353f80,0xbf350000,0xbf353f80,0xbf350000,0x3f350000,0xbf353f80,0x3f350000,0xbf353f80,0x3f35bf80,0x3f350000,0x3f35bf80,0x3f350000,
0xbf350000,0x3f35bf80,0xbf350000,0x3f35bf80,0xbf463f80,0xbf220000,0xbf7f3f35,0x3dc9bf35,0x3ef13e48,0xbf623f7b,0xbe953f55,0xbf753f0e,
0x3f75bf6d,0x3e953ec4,0x3f62bec4,0xbef13f6d,0xbdc9bf0e,0x3f7fbf55,0x3f22bf7b,0x3f46be48,0xbf553f80,0xbf0e0000,0xbf0e0000,0x3f55bf80,
0x3e483ec4,0xbf7b3f6d,0xbf7b3f6d,0xbe48bec4,0x3f7bbf35,0xbe483f35,0xbe483f35,0xbf7b3f35,0x3f0ebf6d,0x3f55bec4,0x3f55bec4,0xbf0e3f6d,
0xbf623f80,0xbef10000,0x3e95bf35,0x3f75bf35,0xbdc93f0e,0xbf7f3f55,0xbf223e48,0x3f46bf7b,0x3f46bec4,0xbf223f6d,0xbf7f3f6d,0xbdc9bec4,
0x3f75bf7b,0x3e953e48,0xbef13f55,0xbf623f0e,0xbf6d3f80,0xbec40000,0x3f6dbf80,0x3ec40000,0xbec43f35,0xbf6d3f35,0x3ec4bf35,0x3f6dbf35,
0x3ec40000,0xbf6d3f80,0xbec40000,0x3f6dbf80,0x3f6dbf35,0xbec43f35,0xbf6d3f35,0x3ec4bf35,0xbf753f80,0xbe950000,0x3f62bf35,0xbef13f35,
0xbf223f55,0xbf463f0e,0x3f7fbf7b,0x3dc93e48,0xbdc93ec4,0xbf7f3f6d,0x3f46bf6d,0x3f22bec4,0x3ef1be48,0xbf623f7b,0x3e95bf0e,0x3f75bf55,
0xbf7b3f80,0xbe480000,0x3e480000,0xbf7b3f80,0xbf553f6d,0xbf0e3ec4,0x3f0ebec4,0xbf553f6d,0xbf0e3f35,0xbf553f35,0x3f55bf35,0xbf0e3f35,
0xbe483ec4,0xbf7b3f6d,0x3f7bbf6d,0xbe483ec4,0xbf7f3f80,0xbdc90000,0xbf223f35,0xbf463f35,0xbf753f7b,0xbe953e48,0xbef13f0e,0xbf623f55,
0xbf623f6d,0xbef13ec4,0xbe953ec4,0xbf753f6d,0xbf463f55,0xbf223f0e,0xbdc93e48,0xbf7f3f7b,0x3f803f80,0xbf803f80,0x3f803f80,0xbf803f80,
0x3f803f80,0xbf803f80,0x3f803f80,0xbf803f80,0x3f803f80,0xbf803f80,0x3f803f80,0xbf803f80,0x3f803f80,0xbf803f80,0x3f803f80,0xbf803f80,
0xbdc90000,0xbf7fbf80,0xbf46bf35,0xbf22bf35,0xbe95be48,0xbf75bf7b,0xbf62bf55,0xbef1bf0e,0xbef1bec4,0xbf62bf6d,0xbf75bf6d,0xbe95bec4,
0xbf22bf0e,0xbf46bf55,0xbf7fbf7b,0xbdc9be48,0xbf7bbf80,0x3e480000,0x3e480000,0x3f7b3f80,0xbf55bf6d,0x3f0e3ec4,0x3f0e3ec4,0x3f553f6d,
0xbf0ebf35,0x3f553f35,0x3f553f35,0x3f0e3f35,0xbe48bec4,0x3f7b3f6d,0x3f7b3f6d,0x3e483ec4,0x3e950000,0x3f753f80,0x3ef13f35,0xbf62bf35,
0x3f463f0e,0x3f223f55,0xbdc93e48,0xbf7fbf7b,0x3f7f3f6d,0x3dc93ec4,0xbf22bec4,0xbf46bf6d,0x3f623f7b,0xbef1be48,0xbf75bf55,0xbe95bf0e,
0x3f6d3f80,0xbec40000,0xbf6dbf80,0x3ec40000,0x3ec43f35,0xbf6dbf35,0xbec4bf35,0x3f6d3f35,0xbec40000,0xbf6dbf80,0x3ec40000,0x3f6d3f80,
0xbf6dbf35,0xbec4bf35,0x3f6d3f35,0x3ec43f35,0xbef10000,0xbf62bf80,0x3f753f35,0x3e953f35,0xbf7fbf55,0xbdc9bf0e,0x3f463f7b,0xbf22be48,
0xbf22bf6d,0x3f463ec4,0xbdc93ec4,0xbf7fbf6d,0x3e95be48,0x3f753f7b,0xbf62bf0e,0xbef1bf55,0xbf55bf80,0x3f0e0000,0xbf0e0000,0xbf55bf80,
0x3e48bec4,0x3f7b3f6d,0xbf7bbf6d,0x3e48bec4,0x3f7b3f35,0x3e483f35,0xbe48bf35,0x3f7b3f35,0x3f0e3f6d,0xbf55bec4,0x3f553ec4,0x3f0e3f6d,
0x3f220000,0x3f463f80,0xbdc9bf35,0x3f7f3f35,0x3f623f7b,0xbef13e48,0x3f753f0e,0x3e953f55,0xbe953ec4,0xbf75bf6d,0x3ef13f6d,0xbf62bec4,
0xbf7fbf55,0x3dc9bf0e,0xbf46be48,0xbf22bf7b,0x3f353f80,0xbf350000,0x3f353f80,0xbf350000,0xbf350000,0xbf35bf80,0xbf350000,0xbf35bf80,
0xbf35bf80,0x3f350000,0xbf35bf80,0x3f350000,0x3f350000,0x3f353f80,0x3f350000,0x3f353f80,0xbf460000,0xbf22bf80,0xbf7fbf35,0x3dc9bf35,
0xbef1bf7b,0x3f623e48,0x3e95bf0e,0x3f753f55,0x3f753ec4,0x3e953f6d,0x3f623f6d,0xbef13ec4,0x3dc93f55,0xbf7fbf0e,0xbf223e48,0xbf46bf7b,
0xbf0ebf80,0x3f550000,0x3f550000,0x3f0e3f80,0x3f7b3ec4,0x3e483f6d,0x3e483f6d,0xbf7bbec4,0xbe483f35,0xbf7bbf35,0xbf7bbf35,0x3e48bf35,
0xbf55bf6d,0x3f0ebec4,0x3f0ebec4,0x3f553f6d,0x3f620000,0x3ef13f80,0xbe953f35,0xbf75bf35,0xbdc93f55,0xbf7fbf0e,0xbf22bf7b,0x3f46be48,
0xbf46bf6d,0x3f22bec4,0x3f7f3ec4,0x3dc93f6d,0x3f753e48,0x3e953f7b,0xbef13f0e,0xbf62bf55,0x3ec43f80,0xbf6d0000,0xbec4bf80,0x3f6d0000,
0xbf6dbf35,0x3ec4bf35,0x3f6d3f35,0xbec43f35,0x3f6d0000,0x3ec43f80,0xbf6d0000,0xbec4bf80,0xbec43f35,0xbf6dbf35,0x3ec4bf35,0x3f6d3f35,
0xbf750000,0xbe95bf80,0x3f623f35,0xbef13f35,0x3f22bf0e,0x3f463f55,0xbf7fbe48,0xbdc9bf7b,0xbdc93f6d,0xbf7fbec4,0x3f46bec4,0x3f223f6d,
0xbef1bf7b,0x3f62be48,0xbe953f55,0xbf75bf0e,0xbe48bf80,0x3f7b0000,0xbf7b0000,0xbe48bf80,0x3f0e3f6d,0xbf553ec4,0x3f55bec4,0x3f0e3f6d,
0xbf55bf35,0x3f0ebf35,0xbf0e3f35,0xbf55bf35,0x3f7b3ec4,0xbe483f6d,0x3e48bf6d,0x3f7b3ec4,0x3f7f0000,0x3dc93f80,0x3f22bf35,0x3f463f35,
0xbf753e48,0xbe95bf7b,0xbef13f55,0xbf62bf0e,0x3f62bec4,0x3ef13f6d,0x3e95bf6d,0x3f753ec4,0xbf463f0e,0xbf22bf55,0xbdc93f7b,0xbf7fbe48,
0x3f80,0xbf800000,0x3f80,0xbf800000,0xbf80,0x3f800000,0xbf80,0x3f800000,0x3f80,0xbf800000,0x3f80,0xbf800000,
0xbf80,0x3f800000,0xbf80,0x3f800000,0xbf7f0000,0x3dc9bf80,0xbf22bf35,0x3f46bf35,0x3f753e48,0xbe953f7b,0x3ef13f55,0xbf623f0e,
0xbf62bec4,0x3ef1bf6d,0xbe95bf6d,0x3f75bec4,0x3f463f0e,0xbf223f55,0x3dc93f7b,0xbf7f3e48,0x3e48bf80,0x3f7b0000,0x3f7b0000,0xbe483f80,
0xbf0e3f6d,0xbf55bec4,0xbf55bec4,0x3f0ebf6d,0x3f55bf35,0x3f0e3f35,0x3f0e3f35,0xbf553f35,0xbf7b3ec4,0xbe48bf6d,0xbe48bf6d,0x3f7bbec4,
0x3f750000,0xbe953f80,0xbf623f35,0xbef1bf35,0xbf22bf0e,0x3f46bf55,0x3f7fbe48,0xbdc93f7b,0x3dc93f6d,0xbf7f3ec4,0xbf46bec4,0x3f22bf6d,
0x3ef1bf7b,0x3f623e48,0x3e953f55,0xbf753f0e,0xbec43f80,0xbf6d0000,0x3ec4bf80,0x3f6d0000,0x3f6dbf35,0x3ec43f35,0xbf6d3f35,0xbec4bf35,
0xbf6d0000,0x3ec4bf80,0x3f6d0000,0xbec43f80,0x3ec43f35,0xbf6d3f35,0xbec4bf35,0x3f6dbf35,0xbf620000,0x3ef1bf80,0x3e953f35,0xbf753f35,
0x3dc93f55,0xbf7f3f0e,0x3f22bf7b,0x3f463e48,0x3f46bf6d,0x3f223ec4,0xbf7f3ec4,0x3dc9bf6d,0xbf753e48,0x3e95bf7b,0x3ef13f0e,0xbf623f55,
0x3f0ebf80,0x3f550000,0xbf550000,0x3f0ebf80,0xbf7b3ec4,0x3e48bf6d,0xbe483f6d,0xbf7b3ec4,0x3e483f35,0xbf7b3f35,0x3f7bbf35,0x3e483f35,
0x3f55bf6d,0x3f0e3ec4,0xbf0ebec4,0x3f55bf6d,0x3f460000,0xbf223f80,0x3f7fbf35,0x3dc93f35,0x3ef1bf7b,0x3f62be48,0xbe95bf0e,0x3f75bf55,
0xbf753ec4,0x3e95bf6d,0xbf623f6d,0xbef1bec4,0xbdc93f55,0xbf7f3f0e,0x3f223e48,0xbf463f7b,0xbf353f80,0xbf350000,0xbf353f80,0xbf350000,
0x3f350000,0xbf353f80,0x3f350000,0xbf353f80,0x3f35bf80,0x3f350000,0x3f35bf80,0x3f350000,0xbf350000,0x3f35bf80,0xbf350000,0x3f35bf80,
0xbf220000,0x3f46bf80,0x3dc9bf35,0x3f7fbf35,0xbf623f7b,0xbef1be48,0xbf753f0e,0x3e95bf55,0x3e953ec4,0xbf753f6d,0xbef13f6d,0xbf623ec4,
0x3f7fbf55,0x3dc93f0e,0x3f46be48,0xbf223f7b,0x3f55bf80,0x3f0e0000,0x3f0e0000,0xbf553f80,0xbe48bec4,0x3f7bbf6d,0x3f7bbf6d,0x3e483ec4,
0xbf7b3f35,0x3e48bf35,0x3e48bf35,0x3f7bbf35,0xbf0e3f6d,0xbf553ec4,0xbf553ec4,0x3f0ebf6d,0x3ef10000,0xbf623f80,0xbf753f35,0x3e95bf35,
0x3f7fbf55,0xbdc93f0e,0xbf463f7b,0xbf223e48,0x3f22bf6d,0x3f46bec4,0x3dc93ec4,0xbf7f3f6d,0xbe95be48,0x3f75bf7b,0x3f62bf0e,0xbef13f55,
0xbf6d3f80,0xbec40000,0x3f6dbf80,0x3ec40000,0xbec43f35,0xbf6d3f35,0x3ec4bf35,0x3f6dbf35,0x3ec40000,0xbf6d3f80,0xbec40000,0x3f6dbf80,
0x3f6dbf35,0xbec43f35,0xbf6d3f35,0x3ec4bf35,0xbe950000,0x3f75bf80,0xbef13f35,0xbf623f35,0xbf463f0e,0x3f22bf55,0x3dc93e48,0xbf7f3f7b,
0xbf7f3f6d,0x3dc9bec4,0x3f22bec4,0xbf463f6d,0xbf623f7b,0xbef13e48,0x3f75bf55,0xbe953f0e,0x3f7bbf80,0x3e480000,0xbe480000,0x3f7bbf80,
0x3f55bf6d,0x3f0ebec4,0xbf0e3ec4,0x3f55bf6d,0x3f0ebf35,0x3f55bf35,0xbf553f35,0x3f0ebf35,0x3e48bec4,0x3f7bbf6d,0xbf7b3f6d,0x3e48bec4,
0x3dc90000,0xbf7f3f80,0x3f46bf35,0xbf223f35,0x3e95be48,0xbf753f7b,0x3f62bf55,0xbef13f0e,0x3ef1bec4,0xbf623f6d,0x3f75bf6d,0xbe953ec4,
0x3f22bf0e,0xbf463f55,0x3f7fbf7b,0xbdc93e48,0x3f803f80,0xbf803f80,0x3f803f80,0xbf803f80,0x3f803f80,0xbf803f80,0x3f803f80,0xbf803f80,
0x3f803f80,0xbf803f80,0x3f803f80,0xbf803f80,0x3f803f80,0xbf803f80,0x3f803f80,0xbf803f80,0xbf7fbf80,0x3dc90000,0xbf22bf35,0x3f463f35,
0xbf75bf7b,0x3e953e48,0xbef1bf0e,0x3f623f55,0xbf62bf6d,0x3ef13ec4,0xbe95bec4,0x3f753f6d,0xbf46bf55,0x3f223f0e,0xbdc9be48,0x3f7f3f7b,
0x3f7b3f80,0xbe480000,0xbe480000,0xbf7bbf80,0x3f553f6d,0xbf0ebec4,0xbf0ebec4,0xbf55bf6d,0x3f0e3f35,0xbf55bf35,0xbf55bf35,0xbf0ebf35,
0x3e483ec4,0xbf7bbf6d,0xbf7bbf6d,0xbe48bec4,0xbf75bf80,0x3e950000,0x3f623f35,0x3ef13f35,0xbf22bf55,0x3f463f0e,0x3f7f3f7b,0xbdc93e48,
0xbdc9bec4,0x3f7f3f6d,0x3f463f6d,0xbf22bec4,0x3ef13e48,0x3f623f7b,0x3e953f0e,0xbf75bf55,0x3f6d3f80,0xbec40000,0xbf6dbf80,0x3ec40000,
0x3ec43f35,0xbf6dbf35,0xbec4bf35,0x3f6d3f35,0xbec40000,0xbf6dbf80,0x3ec40000,0x3f6d3f80,0xbf6dbf35,0xbec4bf35,0x3f6d3f35,0x3ec43f35,
0xbf62bf80,0x3ef10000,0x3e953f35,0xbf75bf35,0xbdc9bf0e,0x3f7f3f55,0xbf22be48,0xbf46bf7b,0x3f463ec4,0x3f223f6d,0xbf7fbf6d,0x3dc9bec4,
0x3f753f7b,0xbe953e48,0xbef1bf55,0x3f623f0e,0x3f553f80,0xbf0e0000,0x3f0e0000,0x3f553f80,0xbe483ec4,0xbf7bbf6d,0x3f7b3f6d,0xbe483ec4,
0xbf7bbf35,0xbe48bf35,0x3e483f35,0xbf7bbf35,0xbf0ebf6d,0x3f553ec4,0xbf55bec4,0xbf0ebf6d,0xbf46bf80,0x3f220000,0xbf7fbf35,0xbdc9bf35,
0x3ef1be48,0x3f623f7b,0xbe95bf55,0x3f753f0e,0x3f753f6d,0xbe953ec4,0x3f623ec4,0x3ef13f6d,0xbdc93f0e,0xbf7fbf55,0x3f223f7b,0xbf46be48,
0x3f353f80,0xbf350000,0x3f353f80,0xbf350000,0xbf350000,0xbf35bf80,0xbf350000,0xbf35bf80,0xbf35bf80,0x3f350000,0xbf35bf80,0x3f350000,
0x3f350000,0x3f353f80,0x3f350000,0x3f353f80,0xbf22bf80,0x3f460000,0x3dc9bf35,0x3f7f3f35,0x3f623e48,0x3ef13f7b,0x3f753f55,0xbe953f0e,
0x3e953f6d,0xbf75bec4,0xbef13ec4,0xbf62bf6d,0xbf7fbf0e,0xbdc9bf55,0xbf46bf7b,0x3f22be48,0x3f0e3f80,0xbf550000,0xbf550000,0xbf0ebf80,
0xbf7bbec4,0xbe48bf6d,0xbe48bf6d,0x3f7b3ec4,0x3e48bf35,0x3f7b3f35,0x3f7b3f35,0xbe483f35,0x3f553f6d,0xbf0e3ec4,0xbf0e3ec4,0xbf55bf6d,
0xbef1bf80,0x3f620000,0x3f753f35,0xbe953f35,0x3f7f3f0e,0xbdc93f55,0xbf463e48,0xbf22bf7b,0xbf223ec4,0xbf46bf6d,0xbdc9bf6d,0x3f7f3ec4,
0xbe95bf7b,0x3f753e48,0x3f623f55,0xbef13f0e,0x3ec43f80,0xbf6d0000,0xbec4bf80,0x3f6d0000,0xbf6dbf35,0x3ec4bf35,0x3f6d3f35,0xbec43f35,
0x3f6d0000,0x3ec43f80,0xbf6d0000,0xbec4bf80,0xbec43f35,0xbf6dbf35,0x3ec4bf35,0x3f6d3f35,0xbe95bf80,0x3f750000,0xbef13f35,0xbf62bf35,
0x3f463f55,0xbf223f0e,0xbdc9bf7b,0x3f7f3e48,0xbf7fbec4,0x3dc9bf6d,0x3f223f6d,0xbf463ec4,0x3f62be48,0x3ef13f7b,0xbf75bf0e,0x3e95bf55,
0x3e483f80,0xbf7b0000,0x3f7b0000,0x3e483f80,0xbf0ebf6d,0x3f55bec4,0xbf553ec4,0xbf0ebf6d,0x3f553f35,0xbf0e3f35,0x3f0ebf35,0x3f553f35,
0xbf7bbec4,0x3e48bf6d,0xbe483f6d,0xbf7bbec4,0xbdc9bf80,0x3f7f0000,0xbf46bf35,0x3f22bf35,0x3e953f7b,0xbf753e48,0x3f623f0e,0xbef13f55,
0xbef1bf6d,0x3f62bec4,0xbf75bec4,0x3e95bf6d,0x3f223f55,0xbf463f0e,0x3f7f3e48,0xbdc93f7b,0x3f80,0xbf800000,0x3f80,0xbf800000,
0xbf80,0x3f800000,0xbf80,0x3f800000,0x3f80,0xbf800000,0x3f80,0xbf800000,0xbf80,0x3f800000,0xbf80,0x3f800000,
0x3dc9bf80,0x3f7f0000,0x3f46bf35,0x3f223f35,0xbe953f7b,0xbf75be48,0xbf623f0e,0xbef1bf55,0x3ef1bf6d,0x3f623ec4,0x3f75bec4,0x3e953f6d,
0xbf223f55,0xbf46bf0e,0xbf7f3e48,0xbdc9bf7b,0xbe483f80,0xbf7b0000,0xbf7b0000,0x3e48bf80,0x3f0ebf6d,0x3f553ec4,0x3f553ec4,0xbf0e3f6d,
0xbf553f35,0xbf0ebf35,0xbf0ebf35,0x3f55bf35,0x3f7bbec4,0x3e483f6d,0x3e483f6d,0xbf7b3ec4,0x3e95bf80,0x3f750000,0x3ef13f35,0xbf623f35,
0xbf463f55,0xbf22bf0e,0x3dc9bf7b,0x3f7fbe48,0x3f7fbec4,0x3dc93f6d,0xbf223f6d,0xbf46bec4,0xbf62be48,0x3ef1bf7b,0x3f75bf0e,0x3e953f55,
0xbec43f80,0xbf6d0000,0x3ec4bf80,0x3f6d0000,0x3f6dbf35,0x3ec43f35,0xbf6d3f35,0xbec4bf35,0xbf6d0000,0x3ec4bf80,0x3f6d0000,0xbec43f80,
0x3ec43f35,0xbf6d3f35,0xbec4bf35,0x3f6dbf35,0x3ef1bf80,0x3f620000,0xbf753f35,0xbe95bf35,0xbf7f3f0e,0xbdc9bf55,0x3f463e48,0xbf223f7b,
0x3f223ec4,0xbf463f6d,0x3dc9bf6d,0x3f7fbec4,0x3e95bf7b,0x3f75be48,0xbf623f55,0xbef1bf0e,0xbf0e3f80,0xbf550000,0x3f550000,0xbf0e3f80,
0x3f7bbec4,0xbe483f6d,0x3e48bf6d,0x3f7bbec4,0xbe48bf35,0x3f7bbf35,0xbf7b3f35,0xbe48bf35,0xbf553f6d,0xbf0ebec4,0x3f0e3ec4,0xbf553f6d,
0x3f22bf80,0x3f460000,0xbdc9bf35,0x3f7fbf35,0xbf623e48,0x3ef1bf7b,0xbf753f55,0xbe95bf0e,0xbe953f6d,0xbf753ec4,0x3ef13ec4,0xbf623f6d,
0x3f7fbf0e,0xbdc93f55,0x3f46bf7b,0x3f223e48,0xbf353f80,0xbf350000,0xbf353f80,0xbf350000,0x3f350000,0xbf353f80,0x3f350000,0xbf353f80,
0x3f35bf80,0x3f350000,0x3f35bf80,0x3f350000,0xbf350000,0x3f35bf80,0xbf350000,0x3f35bf80,0x3f46bf80,0x3f220000,0x3f7fbf35,0xbdc93f35,
0xbef1be48,0x3f62bf7b,0x3e95bf55,0x3f75bf0e,0xbf753f6d,0xbe95bec4,0xbf623ec4,0x3ef1bf6d,0x3dc93f0e,0xbf7f3f55,0xbf223f7b,0xbf463e48,
0xbf553f80,0xbf0e0000,0xbf0e0000,0x3f55bf80,0x3e483ec4,0xbf7b3f6d,0xbf7b3f6d,0xbe48bec4,0x3f7bbf35,0xbe483f35,0xbe483f35,0xbf7b3f35,
0x3f0ebf6d,0x3f55bec4,0x3f55bec4,0xbf0e3f6d,0x3f62bf80,0x3ef10000,0xbe953f35,0xbf753f35,0x3dc9bf0e,0x3f7fbf55,0x3f22be48,0xbf463f7b,
0xbf463ec4,0x3f22bf6d,0x3f7fbf6d,0x3dc93ec4,0xbf753f7b,0xbe95be48,0x3ef1bf55,0x3f62bf0e,0xbf6d3f80,0xbec40000,0x3f6dbf80,0x3ec40000,
0xbec43f35,0xbf6d3f35,0x3ec4bf35,0x3f6dbf35,0x3ec40000,0xbf6d3f80,0xbec40000,0x3f6dbf80,0x3f6dbf35,0xbec43f35,0xbf6d3f35,0x3ec4bf35,
0x3f75bf80,0x3e950000,0xbf623f35,0x3ef1bf35,0x3f22bf55,0x3f46bf0e,0xbf7f3f7b,0xbdc9be48,0x3dc9bec4,0x3f7fbf6d,0xbf463f6d,0xbf223ec4,
0xbef13e48,0x3f62bf7b,0xbe953f0e,0xbf753f55,0xbf7b3f80,0xbe480000,0x3e480000,0xbf7b3f80,0xbf553f6d,0xbf0e3ec4,0x3f0ebec4,0xbf553f6d,
0xbf0e3f35,0xbf553f35,0x3f55bf35,0xbf0e3f35,0xbe483ec4,0xbf7b3f6d,0x3f7bbf6d,0xbe483ec4,0x3f7fbf80,0x3dc90000,0x3f22bf35,0x3f46bf35,
0x3f75bf7b,0x3e95be48,0x3ef1bf0e,0x3f62bf55,0x3f62bf6d,0x3ef1bec4,0x3e95bec4,0x3f75bf6d,0x3f46bf55,0x3f22bf0e,0x3dc9be48,0x3f7fbf7b,
0x3f803f80,0xbf803f80,0x3f803f80,0xbf803f80,0x3f803f80,0xbf803f80,0x3f803f80,0xbf803f80,0x3f803f80,0xbf803f80,0x3f803f80,0xbf803f80,
0x3f803f80,0xbf803f80,0x3f803f80,0xbf803f80,0x3dc90000,0x3f7f3f80,0x3f463f35,0x3f223f35,0x3e953e48,0x3f753f7b,0x3f623f55,0x3ef13f0e,
0x3ef13ec4,0x3f623f6d,0x3f753f6d,0x3e953ec4,0x3f223f0e,0x3f463f55,0x3f7f3f7b,0x3dc93e48,0xbf7bbf80,0x3e480000,0x3e480000,0x3f7b3f80,
0xbf55bf6d,0x3f0e3ec4,0x3f0e3ec4,0x3f553f6d,0xbf0ebf35,0x3f553f35,0x3f553f35,0x3f0e3f35,0xbe48bec4,0x3f7b3f6d,0x3f7b3f6d,0x3e483ec4,
0xbe950000,0xbf75bf80,0xbef1bf35,0x3f623f35,0xbf46bf0e,0xbf22bf55,0x3dc9be48,0x3f7f3f7b,0xbf7fbf6d,0xbdc9bec4,0x3f223ec4,0x3f463f6d,
0xbf62bf7b,0x3ef13e48,0x3f753f55,0x3e953f0e,0x3f6d3f80,0xbec40000,0xbf6dbf80,0x3ec40000,0x3ec43f35,0xbf6dbf35,0xbec4bf35,0x3f6d3f35,
0xbec40000,0xbf6dbf80,0x3ec40000,0x3f6d3f80,0xbf6dbf35,0xbec4bf35,0x3f6d3f35,0x3ec43f35,0x3ef10000,0x3f623f80,0xbf75bf35,0xbe95bf35,
0x3f7f3f55,0x3dc93f0e,0xbf46bf7b,0x3f223e48,0x3f223f6d,0xbf46bec4,0x3dc9bec4,0x3f7f3f6d,0xbe953e48,0xbf75bf7b,0x3f623f0e,0x3ef13f55,
0xbf55bf80,0x3f0e0000,0xbf0e0000,0xbf55bf80,0x3e48bec4,0x3f7b3f6d,0xbf7bbf6d,0x3e48bec4,0x3f7b3f35,0x3e483f35,0xbe48bf35,0x3f7b3f35,
0x3f0e3f6d,0xbf55bec4,0x3f553ec4,0x3f0e3f6d,0xbf220000,0xbf46bf80,0x3dc93f35,0xbf7fbf35,0xbf62bf7b,0x3ef1be48,0xbf75bf0e,0xbe95bf55,
0x3e95bec4,0x3f753f6d,0xbef1bf6d,0x3f623ec4,0x3f7f3f55,0xbdc93f0e,0x3f463e48,0x3f223f7b,0x3f353f80,0xbf350000,0x3f353f80,0xbf350000,
0xbf350000,0xbf35bf80,0xbf350000,0xbf35bf80,0xbf35bf80,0x3f350000,0xbf35bf80,0x3f350000,0x3f350000,0x3f353f80,0x3f350000,0x3f353f80,
0x3f460000,0x3f223f80,0x3f7f3f35,0xbdc93f35,0x3ef13f7b,0xbf62be48,0xbe953f0e,0xbf75bf55,0xbf75bec4,0xbe95bf6d,0xbf62bf6d,0x3ef1bec4,
0xbdc9bf55,0x3f7f3f0e,0x3f22be48,0x3f463f7b,0xbf0ebf80,0x3f550000,0x3f550000,0x3f0e3f80,0x3f7b3ec4,0x3e483f6d,0x3e483f6d,0xbf7bbec4,
0xbe483f35,0xbf7bbf35,0xbf7bbf35,0x3e48bf35,0xbf55bf6d,0x3f0ebec4,0x3f0ebec4,0x3f553f6d,0xbf620000,0xbef1bf80,0x3e95bf35,0x3f753f35,
0x3dc9bf55,0x3f7f3f0e,0x3f223f7b,0xbf463e48,0x3f463f6d,0xbf223ec4,0xbf7fbec4,0xbdc9bf6d,0xbf75be48,0xbe95bf7b,0x3ef1bf0e,0x3f623f55,
0x3ec43f80,0xbf6d0000,0xbec4bf80,0x3f6d0000,0xbf6dbf35,0x3ec4bf35,0x3f6d3f35,0xbec43f35,0x3f6d0000,0x3ec43f80,0xbf6d0000,0xbec4bf80,
0xbec43f35,0xbf6dbf35,0x3ec4bf35,0x3f6d3f35,0x3f750000,0x3e953f80,0xbf62bf35,0x3ef1bf35,0xbf223f0e,0xbf46bf55,0x3f7f3e48,0x3dc93f7b,
0x3dc9bf6d,0x3f7f3ec4,0xbf463ec4,0xbf22bf6d,0x3ef13f7b,0xbf623e48,0x3e95bf55,0x3f753f0e,0xbe48bf80,0x3f7b0000,0xbf7b0000,0xbe48bf80,
0x3f0e3f6d,0xbf553ec4,0x3f55bec4,0x3f0e3f6d,0xbf55bf35,0x3f0ebf35,0xbf0e3f35,0xbf55bf35,0x3f7b3ec4,0xbe483f6d,0x3e48bf6d,0x3f7b3ec4,
0xbf7f0000,0xbdc9bf80,0xbf223f35,0xbf46bf35,0x3f75be48,0x3e953f7b,0x3ef1bf55,0x3f623f0e,0xbf623ec4,0xbef1bf6d,0xbe953f6d,0xbf75bec4,
0x3f46bf0e,0x3f223f55,0x3dc9bf7b,0x3f7f3e48,0x3f80,0xbf800000,0x3f80,0xbf800000,0xbf80,0x3f800000,0xbf80,0x3f800000,
0x3f80,0xbf800000,0x3f80,0xbf800000,0xbf80,0x3f800000,0xbf80,0x3f800000,0x3f7f0000,0xbdc93f80,0x3f223f35,0xbf463f35,
0xbf75be48,0x3e95bf7b,0xbef1bf55,0x3f62bf0e,0x3f623ec4,0xbef13f6d,0x3e953f6d,0xbf753ec4,0xbf46bf0e,0x3f22bf55,0xbdc9bf7b,0x3f7fbe48,
0x3e48bf80,0x3f7b0000,0x3f7b0000,0xbe483f80,0xbf0e3f6d,0xbf55bec4,0xbf55bec4,0x3f0ebf6d,0x3f55bf35,0x3f0e3f35,0x3f0e3f35,0xbf553f35,
0xbf7b3ec4,0xbe48bf6d,0xbe48bf6d,0x3f7bbec4,0xbf750000,0x3e95bf80,0x3f62bf35,0x3ef13f35,0x3f223f0e,0xbf463f55,0xbf7f3e48,0x3dc9bf7b,
0xbdc9bf6d,0x3f7fbec4,0x3f463ec4,0xbf223f6d,0xbef13f7b,0xbf62be48,0xbe95bf55,0x3f75bf0e,0xbec43f80,0xbf6d0000,0x3ec4bf80,0x3f6d0000,
0x3f6dbf35,0x3ec43f35,0xbf6d3f35,0xbec4bf35,0xbf6d0000,0x3ec4bf80,0x3f6d0000,0xbec43f80,0x3ec43f35,0xbf6d3f35,0xbec4bf35,0x3f6dbf35,
0x3f620000,0xbef13f80,0xbe95bf35,0x3f75bf35,0xbdc9bf55,0x3f7fbf0e,0xbf223f7b,0xbf46be48,0xbf463f6d,0xbf22bec4,0x3f7fbec4,0xbdc93f6d,
0x3f75be48,0xbe953f7b,0xbef1bf0e,0x3f62bf55,0x3f0ebf80,0x3f550000,0xbf550000,0x3f0ebf80,0xbf7b3ec4,0x3e48bf6d,0xbe483f6d,0xbf7b3ec4,
0x3e483f35,0xbf7b3f35,0x3f7bbf35,0x3e483f35,0x3f55bf6d,0x3f0e3ec4,0xbf0ebec4,0x3f55bf6d,0xbf460000,0x3f22bf80,0xbf7f3f35,0xbdc9bf35,
0xbef13f7b,0xbf623e48,0x3e953f0e,0xbf753f55,0x3f75bec4,0xbe953f6d,0x3f62bf6d,0x3ef13ec4,0x3dc9bf55,0x3f7fbf0e,0xbf22be48,0x3f46bf7b,
0xbf353f80,0xbf350000,0xbf353f80,0xbf350000,0x3f350000,0xbf353f80,0x3f350000,0xbf353f80,0x3f35bf80,0x3f350000,0x3f35bf80,0x3f350000,
0xbf350000,0x3f35bf80,0xbf350000,0x3f35bf80,0x3f220000,0xbf463f80,0xbdc93f35,0xbf7f3f35,0x3f62bf7b,0x3ef13e48,0x3f75bf0e,0xbe953f55,
0xbe95bec4,0x3f75bf6d,0x3ef1bf6d,0x3f62bec4,0xbf7f3f55,0xbdc9bf0e,0xbf463e48,0x3f22bf7b,0x3f55bf80,0x3f0e0000,0x3f0e0000,0xbf553f80,
0xbe48bec4,0x3f7bbf6d,0x3f7bbf6d,0x3e483ec4,0xbf7b3f35,0x3e48bf35,0x3e48bf35,0x3f7bbf35,0xbf0e3f6d,0xbf553ec4,0xbf553ec4,0x3f0ebf6d,
0xbef10000,0x3f62bf80,0x3f75bf35,0xbe953f35,0xbf7f3f55,0x3dc9bf0e,0x3f46bf7b,0x3f22be48,0xbf223f6d,0xbf463ec4,0xbdc9bec4,0x3f7fbf6d,
0x3e953e48,0xbf753f7b,0xbf623f0e,0x3ef1bf55,0xbf6d3f80,0xbec40000,0x3f6dbf80,0x3ec40000,0xbec43f35,0xbf6d3f35,0x3ec4bf35,0x3f6dbf35,
0x3ec40000,0xbf6d3f80,0xbec40000,0x3f6dbf80,0x3f6dbf35,0xbec43f35,0xbf6d3f35,0x3ec4bf35,0x3e950000,0xbf753f80,0x3ef1bf35,0x3f62bf35,
0x3f46bf0e,0xbf223f55,0xbdc9be48,0x3f7fbf7b,0x3f7fbf6d,0xbdc93ec4,0xbf223ec4,0x3f46bf6d,0x3f62bf7b,0x3ef1be48,0xbf753f55,0x3e95bf0e,
0x3f7bbf80,0x3e480000,0xbe480000,0x3f7bbf80,0x3f55bf6d,0x3f0ebec4,0xbf0e3ec4,0x3f55bf6d,0x3f0ebf35,0x3f55bf35,0xbf553f35,0x3f0ebf35,
0x3e48bec4,0x3f7bbf6d,0xbf7b3f6d,0x3e48bec4,0xbdc90000,0x3f7fbf80,0xbf463f35,0x3f22bf35,0xbe953e48,0x3f75bf7b,0xbf623f55,0x3ef1bf0e,
0xbef13ec4,0x3f62bf6d,0xbf753f6d,0x3e95bec4,0xbf223f0e,0x3f46bf55,0xbf7f3f7b,0x3dc9be48,0x40003f80,0x3fb53f80,0x3f80,0xbfb53f80,
0x40004000,0xbfb50000,0x0,0xbfb5c000,0x40004000,0xbfb5c000,0x0,0x3fb50000,0x40004000,0x3fb50000,0x0,0x3fb54000,
0x3fff3f80,0x3fa23f80,0xbe49bf80,0xbfc6bf80,0x3ff53ffb,0xbfe2bec8,0xbf15bec8,0xbf71bffb,0x3fe23fed,0xbf15bfed,0xbf71bf44,0x3ff53f44,
0x3fc63fd5,0x3fff3f8e,0xbfa2bf8e,0x3e493fd5,0x3ffb3f80,0x3f8e3f80,0xbec83f80,0xbfd53f80,0x3fd53fed,0xbffbbf44,0xbf8ebf44,0xbec8bfed,
0x3f8e3fb5,0x3ec8bfb5,0xbfd5bfb5,0x3ffb3fb5,0x3ec83f44,0x3fd53fed,0xbffbbfed,0xbf8e3f44,0x3ff53f80,0x3f713f80,0xbf15bf80,0xbfe2bf80,
0x3fa23fd5,0xbfffbf8e,0xbfc6bf8e,0x3e49bfd5,0x3e493f44,0x3fa2bf44,0xbfffbfed,0x3fc63fed,0xbf71bec8,0x3f153ffb,0xbfe2bffb,0xbff5bec8,
0x3fed3f80,0x3f443f80,0xbf443f80,0xbfed3f80,0x3f443fb5,0xbfedbfb5,0xbfedbfb5,0x3f44bfb5,0xbf440000,0x3fed0000,0xbfedc000,0x3f444000,
0xbfedbfb5,0xbf443fb5,0xbf44bfb5,0xbfedbfb5,0x3fe23f80,0x3f153f80,0xbf71bf80,0xbff5bf80,0x3e493f8e,0xbfc6bfd5,0xbfffbfd5,0x3fa2bf8e,
0xbfc6bf44,0x3fff3f44,0xbfa2bfed,0xbe493fed,0xbff5bffb,0xbfe23ec8,0x3f15bec8,0xbf71bffb,0x3fd53f80,0x3ec83f80,0xbf8e3f80,0xbffb3f80,
0xbec83f44,0xbf8ebfed,0xbffbbfed,0x3fd5bf44,0xbffbbfb5,0x3fd53fb5,0xbec8bfb5,0xbf8e3fb5,0xbf8ebfed,0xbffbbf44,0x3fd53f44,0x3ec8bfed,
0x3fc63f80,0x3e493f80,0xbfa2bf80,0xbfffbf80,0xbf713ec8,0xbf15bffb,0xbfe2bffb,0x3ff5bec8,0xbff5bfed,0x3f713fed,0x3f15bf44,0xbfe23f44,
0x3e49bf8e,0xbfa2bfd5,0x3fff3fd5,0x3fc6bf8e,0x3f80,0xbfb53f80,0xc0003f80,0xbfb53f80,0xc000,0x3fb50000,0x40000000,0xbfb54000,
0x4000,0x3fb5c000,0xc0000000,0x3fb50000,0xc000,0xbfb50000,0x40000000,0x3fb5c000,0xbe493f80,0xbfc63f80,0xbfffbf80,0xbfa2bf80,
0x3f15bffb,0x3f713ec8,0x3ff53ec8,0xbfe23ffb,0xbf713fed,0x3ff5bfed,0xbfe2bf44,0x3f153f44,0x3fa2bfd5,0xbe49bf8e,0x3fc63f8e,0x3fffbfd5,
0xbec83f80,0xbfd53f80,0xbffb3f80,0xbf8e3f80,0x3f8ebfed,0x3ec83f44,0x3fd53f44,0xbffb3fed,0xbfd53fb5,0x3ffbbfb5,0xbf8ebfb5,0xbec83fb5,
0x3ffbbf44,0x3f8ebfed,0x3ec83fed,0x3fd5bf44,0xbf153f80,0xbfe23f80,0xbff5bf80,0xbf71bf80,0x3fc6bfd5,0xbe493f8e,0x3fa23f8e,0xbfff3fd5,
0xbfff3f44,0x3fc6bf44,0xbe49bfed,0xbfa23fed,0x3fe23ec8,0x3ff5bffb,0xbf713ffb,0x3f153ec8,0xbf443f80,0xbfed3f80,0xbfed3f80,0xbf443f80,
0x3fedbfb5,0xbf443fb5,0x3f443fb5,0xbfed3fb5,0xbfed0000,0x3f440000,0x3f44c000,0xbfed4000,0x3f443fb5,0x3fedbfb5,0xbfed3fb5,0xbf443fb5,
0xbf713f80,0xbff53f80,0xbfe2bf80,0xbf15bf80,0x3fffbf8e,0xbfa23fd5,0x3e493fd5,0xbfc63f8e,0xbfa2bf44,0xbe493f44,0x3fc6bfed,0xbfff3fed,
0xbf153ffb,0x3f71bec8,0xbff53ec8,0xbfe23ffb,0xbf8e3f80,0xbffb3f80,0xbfd53f80,0xbec83f80,0x3ffbbf44,0xbfd53fed,0xbec83fed,0xbf8e3f44,
0xbec8bfb5,0xbf8e3fb5,0x3ffbbfb5,0xbfd53fb5,0xbfd53fed,0xbec83f44,0xbf8ebf44,0xbffb3fed,0xbfa23f80,0xbfff3f80,0xbfc6bf80,0xbe49bf80,
0x3fe2bec8,0xbff53ffb,0xbf713ffb,0xbf153ec8,0x3f15bfed,0xbfe23fed,0x3ff5bf44,0xbf713f44,0xbfff3f8e,0xbfc63fd5,0x3e49bfd5,0xbfa23f8e,
0xc0003f80,0xbfb53f80,0x3f80,0x3fb53f80,0xc0004000,0x3fb50000,0x0,0x3fb5c000,0xc0004000,0x3fb5c000,0x0,0xbfb50000,
0xc0004000,0xbfb50000,0x0,0xbfb54000,0xbfff3f80,0xbfa23f80,0x3e49bf80,0x3fc6bf80,0xbff53ffb,0x3fe2bec8,0x3f15bec8,0x3f71bffb,
0xbfe23fed,0x3f15bfed,0x3f71bf44,0xbff53f44,0xbfc63fd5,0xbfff3f8e,0x3fa2bf8e,0xbe493fd5,0xbffb3f80,0xbf8e3f80,0x3ec83f80,0x3fd53f80,
0xbfd53fed,0x3ffbbf44,0x3f8ebf44,0x3ec8bfed,0xbf8e3fb5,0xbec8bfb5,0x3fd5bfb5,0xbffb3fb5,0xbec83f44,0xbfd53fed,0x3ffbbfed,0x3f8e3f44,
0xbff53f80,0xbf713f80,0x3f15bf80,0x3fe2bf80,0xbfa23fd5,0x3fffbf8e,0x3fc6bf8e,0xbe49bfd5,0xbe493f44,0xbfa2bf44,0x3fffbfed,0xbfc63fed,
0x3f71bec8,0xbf153ffb,0x3fe2bffb,0x3ff5bec8,0xbfed3f80,0xbf443f80,0x3f443f80,0x3fed3f80,0xbf443fb5,0x3fedbfb5,0x3fedbfb5,0xbf44bfb5,
0x3f440000,0xbfed0000,0x3fedc000,0xbf444000,0x3fedbfb5,0x3f443fb5,0x3f44bfb5,0x3fedbfb5,0xbfe23f80,0xbf153f80,0x3f71bf80,0x3ff5bf80,
0xbe493f8e,0x3fc6bfd5,0x3fffbfd5,0xbfa2bf8e,0x3fc6bf44,0xbfff3f44,0x3fa2bfed,0x3e493fed,0x3ff5bffb,0x3fe23ec8,0xbf15bec8,0x3f71bffb,
0xbfd53f80,0xbec83f80,0x3f8e3f80,0x3ffb3f80,0x3ec83f44,0x3f8ebfed,0x3ffbbfed,0xbfd5bf44,0x3ffbbfb5,0xbfd53fb5,0x3ec8bfb5,0x3f8e3fb5,
0x3f8ebfed,0x3ffbbf44,0xbfd53f44,0xbec8bfed,0xbfc63f80,0xbe493f80,0x3fa2bf80,0x3fffbf80,0x3f713ec8,0x3f15bffb,0x3fe2bffb,0xbff5bec8,
0x3ff5bfed,0xbf713fed,0xbf15bf44,0x3fe23f44,0xbe49bf8e,0x3fa2bfd5,0xbfff3fd5,0xbfc6bf8e,0x3f80,0x3fb53f80,0x40003f80,0x3fb53f80,
0xc000,0xbfb50000,0xc0000000,0x3fb54000,0x4000,0xbfb5c000,0x40000000,0xbfb50000,0xc000,0x3fb50000,0xc0000000,0xbfb5c000,
0x3e493f80,0x3fc63f80,0x3fffbf80,0x3fa2bf80,0xbf15bffb,0xbf713ec8,0xbff53ec8,0x3fe23ffb,0x3f713fed,0xbff5bfed,0x3fe2bf44,0xbf153f44,
0xbfa2bfd5,0x3e49bf8e,0xbfc63f8e,0xbfffbfd5,0x3ec83f80,0x3fd53f80,0x3ffb3f80,0x3f8e3f80,0xbf8ebfed,0xbec83f44,0xbfd53f44,0x3ffb3fed,
0x3fd53fb5,0xbffbbfb5,0x3f8ebfb5,0x3ec83fb5,0xbffbbf44,0xbf8ebfed,0xbec83fed,0xbfd5bf44,0x3f153f80,0x3fe23f80,0x3ff5bf80,0x3f71bf80,
0xbfc6bfd5,0x3e493f8e,0xbfa23f8e,0x3fff3fd5,0x3fff3f44,0xbfc6bf44,0x3e49bfed,0x3fa23fed,0xbfe23ec8,0xbff5bffb,0x3f713ffb,0xbf153ec8,
0x3f443f80,0x3fed3f80,0x3fed3f80,0x3f443f80,0xbfedbfb5,0x3f443fb5,0xbf443fb5,0x3fed3fb5,0x3fed0000,0xbf440000,0xbf44c000,0x3fed4000,
0xbf443fb5,0xbfedbfb5,0x3fed3fb5,0x3f443fb5,0x3f713f80,0x3ff53f80,0x3fe2bf80,0x3f15bf80,0xbfffbf8e,0x3fa23fd5,0xbe493fd5,0x3fc63f8e,
0x3fa2bf44,0x3e493f44,0xbfc6bfed,0x3fff3fed,0x3f153ffb,0xbf71bec8,0x3ff53ec8,0x3fe23ffb,0x3f8e3f80,0x3ffb3f80,0x3fd53f80,0x3ec83f80,
0xbffbbf44,0x3fd53fed,0x3ec83fed,0x3f8e3f44,0x3ec8bfb5,0x3f8e3fb5,0xbffbbfb5,0x3fd53fb5,0x3fd53fed,0x3ec83f44,0x3f8ebf44,0x3ffb3fed,
0x3fa23f80,0x3fff3f80,0x3fc6bf80,0x3e49bf80,0xbfe2bec8,0x3ff53ffb,0x3f713ffb,0x3f153ec8,0xbf15bfed,0x3fe23fed,0xbff5bf44,0x3f713f44,
0x3fff3f8e,0x3fc63fd5,0xbe49bfd5,0x3fa23f8e,0x40004000,0x3fb54000,0x0,0xbfb50000,0x40004000,0xbfb50000,0x0,0xbfb5c000,
0x40004000,0xbfb5c000,0x0,0x3fb50000,0x40004000,0x3fb50000,0x0,0x3fb54000,0x3fa23fb5,0xbe493fb5,0xbfc6bfb5,0xbfffbfb5,
0x3f713f8e,0xbff5bfd5,0xbfe2bfd5,0x3f15bf8e,0x3f153f44,0x3f71bf44,0xbff5bfed,0x3fe23fed,0x3e493ec8,0x3fc63ffb,0xbfffbffb,0xbfa23ec8,
0xbec80000,0xbfd50000,0xbffbc000,0xbf8ec000,0xbf8ebf44,0xbec8bfed,0xbfd5bfed,0x3ffb3f44,0xbfd5bfb5,0x3ffb3fb5,0xbf8ebfb5,0xbec83fb5,
0xbffbbfed,0xbf8e3f44,0xbec8bf44,0xbfd5bfed,0xbfe2bfb5,0xbff5bfb5,0xbf71bfb5,0x3f15bfb5,0xbfffbffb,0x3fc6bec8,0x3e49bec8,0x3fa23ffb,
0xbfc6bfed,0x3e493fed,0x3fa23f44,0xbfffbf44,0xbf15bf8e,0xbfe2bfd5,0x3ff53fd5,0x3f71bf8e,0xbfedc000,0xbf44c000,0x3f440000,0x3fed0000,
0xbf44bfb5,0x3fed3fb5,0x3fed3fb5,0xbf443fb5,0x3f440000,0xbfed0000,0x3fed4000,0xbf44c000,0x3fed3fb5,0x3f44bfb5,0x3f443fb5,0x3fed3fb5,
0xbf15bfb5,0x3f71bfb5,0x3ff53fb5,0x3fe23fb5,0x3fa23ec8,0x3e493ffb,0x3fc63ffb,0xbfffbec8,0x3fff3fed,0xbfa2bfed,0xbe493f44,0x3fc6bf44,
0x3f713fd5,0x3ff53f8e,0xbfe2bf8e,0xbf153fd5,0x3f8e0000,0x3ffb0000,0x3fd54000,0x3ec84000,0x3ffb3fed,0xbfd53f44,0xbec83f44,0xbf8ebfed,
0x3ec83fb5,0x3f8ebfb5,0xbffbbfb5,0x3fd53fb5,0xbfd5bf44,0xbec83fed,0xbf8ebfed,0xbffbbf44,0x3fff3fb5,0x3fc63fb5,0x3e493fb5,0xbfa23fb5,
0x3f153fd5,0xbfe2bf8e,0xbff5bf8e,0x3f71bfd5,0xbfe2bf44,0x3ff53f44,0xbf71bfed,0xbf153fed,0xbfa2bffb,0xbfffbec8,0x3fc63ec8,0x3e49bffb,
0x4000,0xbfb54000,0xc0000000,0xbfb50000,0xc000,0x3fb50000,0x40000000,0xbfb54000,0x4000,0x3fb5c000,0xc0000000,0x3fb50000,
0xc000,0xbfb50000,0x40000000,0x3fb5c000,0xbfc63fb5,0xbfff3fb5,0xbfa2bfb5,0x3e49bfb5,0x3fe2bf8e,0xbf153fd5,0x3f713fd5,0xbff53f8e,
0xbff53f44,0x3fe2bf44,0xbf15bfed,0xbf713fed,0x3fffbec8,0x3fa2bffb,0x3e493ffb,0x3fc6bec8,0xbffb0000,0xbf8e0000,0x3ec8c000,0x3fd5c000,
0x3fd53f44,0xbffb3fed,0xbf8e3fed,0xbec8bf44,0xbf8ebfb5,0xbec83fb5,0x3fd5bfb5,0xbffb3fb5,0x3ec83fed,0x3fd5bf44,0xbffb3f44,0xbf8e3fed,
0xbf71bfb5,0x3f15bfb5,0x3fe2bfb5,0x3ff5bfb5,0xbe493ffb,0xbfa23ec8,0xbfff3ec8,0x3fc6bffb,0x3fa2bfed,0xbfff3fed,0x3fc63f44,0xbe49bf44,
0xbff53f8e,0xbf713fd5,0xbf15bfd5,0xbfe23f8e,0x3f44c000,0x3fedc000,0x3fed0000,0x3f440000,0xbfed3fb5,0x3f44bfb5,0xbf44bfb5,0x3fedbfb5,
0x3fed0000,0xbf440000,0xbf444000,0x3fedc000,0xbf44bfb5,0xbfed3fb5,0x3fedbfb5,0x3f44bfb5,0x3ff5bfb5,0x3fe2bfb5,0x3f153fb5,0xbf713fb5,
0xbfc6bec8,0x3fffbffb,0x3fa2bffb,0x3e493ec8,0xbe493fed,0x3fc6bfed,0xbfff3f44,0x3fa2bf44,0x3fe2bfd5,0x3f15bf8e,0x3f713f8e,0x3ff5bfd5,
0x3fd50000,0x3ec80000,0xbf8e4000,0xbffb4000,0x3ec8bfed,0x3f8ebf44,0x3ffbbf44,0xbfd53fed,0xbffb3fb5,0x3fd5bfb5,0xbec8bfb5,0xbf8e3fb5,
0x3f8e3f44,0x3ffbbfed,0xbfd53fed,0xbec83f44,0x3e493fb5,0xbfa23fb5,0xbfff3fb5,0xbfc63fb5,0x3ff5bfd5,0xbf713f8e,0x3f153f8e,0xbfe23fd5,
0xbf71bf44,0xbf153f44,0x3fe2bfed,0xbff53fed,0xbfc63ffb,0xbe493ec8,0xbfa2bec8,0xbfff3ffb,0xc0004000,0xbfb54000,0x0,0x3fb50000,
0xc0004000,0x3fb50000,0x0,0x3fb5c000,0xc0004000,0x3fb5c000,0x0,0xbfb50000,0xc0004000,0xbfb50000,0x0,0xbfb54000,
0xbfa23fb5,0x3e493fb5,0x3fc6bfb5,0x3fffbfb5,0xbf713f8e,0x3ff5bfd5,0x3fe2bfd5,0xbf15bf8e,0xbf153f44,0xbf71bf44,0x3ff5bfed,0xbfe23fed,
0xbe493ec8,0xbfc63ffb,0x3fffbffb,0x3fa23ec8,0x3ec80000,0x3fd50000,0x3ffbc000,0x3f8ec000,0x3f8ebf44,0x3ec8bfed,0x3fd5bfed,0xbffb3f44,
0x3fd5bfb5,0xbffb3fb5,0x3f8ebfb5,0x3ec83fb5,0x3ffbbfed,0x3f8e3f44,0x3ec8bf44,0x3fd5bfed,0x3fe2bfb5,0x3ff5bfb5,0x3f71bfb5,0xbf15bfb5,
0x3fffbffb,0xbfc6bec8,0xbe49bec8,0xbfa23ffb,0x3fc6bfed,0xbe493fed,0xbfa23f44,0x3fffbf44,0x3f15bf8e,0x3fe2bfd5,0xbff53fd5,0xbf71bf8e,
0x3fedc000,0x3f44c000,0xbf440000,0xbfed0000,0x3f44bfb5,0xbfed3fb5,0xbfed3fb5,0x3f443fb5,0xbf440000,0x3fed0000,0xbfed4000,0x3f44c000,
0xbfed3fb5,0xbf44bfb5,0xbf443fb5,0xbfed3fb5,0x3f15bfb5,0xbf71bfb5,0xbff53fb5,0xbfe23fb5,0xbfa23ec8,0xbe493ffb,0xbfc63ffb,0x3fffbec8,
0xbfff3fed,0x3fa2bfed,0x3e493f44,0xbfc6bf44,0xbf713fd5,0xbff53f8e,0x3fe2bf8e,0x3f153fd5,0xbf8e0000,0xbffb0000,0xbfd54000,0xbec84000,
0xbffb3fed,0x3fd53f44,0x3ec83f44,0x3f8ebfed,0xbec83fb5,0xbf8ebfb5,0x3ffbbfb5,0xbfd53fb5,0x3fd5bf44,0x3ec83fed,0x3f8ebfed,0x3ffbbf44,
0xbfff3fb5,0xbfc63fb5,0xbe493fb5,0x3fa23fb5,0xbf153fd5,0x3fe2bf8e,0x3ff5bf8e,0xbf71bfd5,0x3fe2bf44,0xbff53f44,0x3f71bfed,0x3f153fed,
0x3fa2bffb,0x3fffbec8,0xbfc63ec8,0xbe49bffb,0x4000,0x3fb54000,0x40000000,0x3fb50000,0xc000,0xbfb50000,0xc0000000,0x3fb54000,
0x4000,0xbfb5c000,0x40000000,0xbfb50000,0xc000,0x3fb50000,0xc0000000,0xbfb5c000,0x3fc63fb5,0x3fff3fb5,0x3fa2bfb5,0xbe49bfb5,
0xbfe2bf8e,0x3f153fd5,0xbf713fd5,0x3ff53f8e,0x3ff53f44,0xbfe2bf44,0x3f15bfed,0x3f713fed,0xbfffbec8,0xbfa2bffb,0xbe493ffb,0xbfc6bec8,
0x3ffb0000,0x3f8e0000,0xbec8c000,0xbfd5c000,0xbfd53f44,0x3ffb3fed,0x3f8e3fed,0x3ec8bf44,0x3f8ebfb5,0x3ec83fb5,0xbfd5bfb5,0x3ffb3fb5,
0xbec83fed,0xbfd5bf44,0x3ffb3f44,0x3f8e3fed,0x3f71bfb5,0xbf15bfb5,0xbfe2bfb5,0xbff5bfb5,0x3e493ffb,0x3fa23ec8,0x3fff3ec8,0xbfc6bffb,
0xbfa2bfed,0x3fff3fed,0xbfc63f44,0x3e49bf44,0x3ff53f8e,0x3f713fd5,0x3f15bfd5,0x3fe23f8e,0xbf44c000,0xbfedc000,0xbfed0000,0xbf440000,
0x3fed3fb5,0xbf44bfb5,0x3f44bfb5,0xbfedbfb5,0xbfed0000,0x3f440000,0x3f444000,0xbfedc000,0x3f44bfb5,0x3fed3fb5,0xbfedbfb5,0xbf44bfb5,
0xbff5bfb5,0xbfe2bfb5,0xbf153fb5,0x3f713fb5,0x3fc6bec8,0xbfffbffb,0xbfa2bffb,0xbe493ec8,0x3e493fed,0xbfc6bfed,0x3fff3f44,0xbfa2bf44,
0xbfe2bfd5,0xbf15bf8e,0xbf713f8e,0xbff5bfd5,0xbfd50000,0xbec80000,0x3f8e4000,0x3ffb4000,0xbec8bfed,0xbf8ebf44,0xbffbbf44,0x3fd53fed,
0x3ffb3fb5,0xbfd5bfb5,0x3ec8bfb5,0x3f8e3fb5,0xbf8e3f44,0xbffbbfed,0x3fd53fed,0x3ec83f44,0xbe493fb5,0x3fa23fb5,0x3fff3fb5,0x3fc63fb5,
0xbff5bfd5,0x3f713f8e,0xbf153f8e,0x3fe23fd5,0x3f71bf44,0x3f153f44,0xbfe2bfed,0x3ff53fed,0x3fc63ffb,0x3e493ec8,0x3fa2bec8,0x3fff3ffb,
0x40004000,0x3fb54000,0x0,0xbfb50000,0x40004000,0xbfb50000,0x0,0xbfb5c000,0x40004000,0xbfb5c000,0x0,0x3fb50000,
0x40004000,0x3fb50000,0x0,0x3fb54000,0xbe490000,0xbfc60000,0xbfffc000,0xbfa2c000,0xbf15bec8,0xbf71bffb,0xbff5bffb,0x3fe23ec8,
0xbf71bf44,0x3ff53f44,0xbfe2bfed,0x3f153fed,0xbfa2bf8e,0x3e493fd5,0xbfc6bfd5,0xbfffbf8e,0xbffbc000,0xbf8ec000,0x3ec80000,0x3fd50000,
0xbfd5bfed,0x3ffb3f44,0x3f8e3f44,0x3ec83fed,0xbf8ebfb5,0xbec83fb5,0x3fd53fb5,0xbffbbfb5,0xbec8bf44,0xbfd5bfed,0x3ffb3fed,0x3f8ebf44,
0x3f150000,0x3fe20000,0x3ff54000,0x3f714000,0x3fc63f8e,0xbe493fd5,0x3fa23fd5,0xbfffbf8e,0x3fff3fed,0xbfc6bfed,0x3e493f44,0x3fa2bf44,
0x3fe23ffb,0x3ff53ec8,0xbf71bec8,0x3f153ffb,0x3fed4000,0x3f444000,0xbf440000,0xbfed0000,0x3f443fb5,0xbfedbfb5,0xbfedbfb5,0x3f44bfb5,
0xbf440000,0x3fed0000,0xbfedc000,0x3f444000,0xbfedbfb5,0xbf443fb5,0xbf44bfb5,0xbfedbfb5,0xbf710000,0xbff50000,0xbfe2c000,0xbf15c000,
0xbfffbfd5,0x3fa2bf8e,0xbe49bf8e,0x3fc63fd5,0xbfa2bfed,0xbe493fed,0x3fc63f44,0xbfffbf44,0x3f15bec8,0xbf71bffb,0x3ff53ffb,0x3fe2bec8,
0xbfd5c000,0xbec8c000,0x3f8e0000,0x3ffb0000,0x3ec8bf44,0x3f8e3fed,0x3ffb3fed,0xbfd53f44,0x3ffb3fb5,0xbfd5bfb5,0x3ec83fb5,0x3f8ebfb5,
0x3f8e3fed,0x3ffb3f44,0xbfd5bf44,0xbec83fed,0x3fa20000,0x3fff0000,0x3fc64000,0x3e494000,0x3fe23ffb,0xbff53ec8,0xbf713ec8,0xbf15bffb,
0xbf153f44,0x3fe2bf44,0xbff5bfed,0x3f713fed,0xbfffbfd5,0xbfc63f8e,0x3e49bf8e,0xbfa2bfd5,0x4000,0xbfb54000,0xc0000000,0xbfb50000,
0xc000,0x3fb50000,0x40000000,0xbfb54000,0x4000,0x3fb5c000,0xc0000000,0x3fb50000,0xc000,0xbfb50000,0x40000000,0x3fb5c000,
0xbfff0000,0xbfa20000,0x3e49c000,0x3fc6c000,0x3ff53ec8,0xbfe23ffb,0xbf153ffb,0xbf71bec8,0xbfe2bf44,0x3f153f44,0x3f71bfed,0xbff53fed,
0x3fc63f8e,0x3fffbfd5,0xbfa23fd5,0x3e493f8e,0x3ec8c000,0x3fd5c000,0x3ffb0000,0x3f8e0000,0xbf8e3fed,0xbec8bf44,0xbfd5bf44,0x3ffbbfed,
0x3fd5bfb5,0xbffb3fb5,0x3f8e3fb5,0x3ec8bfb5,0xbffb3f44,0xbf8e3fed,0xbec8bfed,0xbfd53f44,0x3ff50000,0x3f710000,0xbf154000,0xbfe24000,
0xbfa2bf8e,0x3fffbfd5,0x3fc6bfd5,0xbe493f8e,0x3e493fed,0x3fa2bfed,0xbfff3f44,0x3fc6bf44,0x3f71bffb,0xbf15bec8,0x3fe23ec8,0x3ff5bffb,
0xbf444000,0xbfed4000,0xbfed0000,0xbf440000,0x3fedbfb5,0xbf443fb5,0x3f443fb5,0xbfed3fb5,0xbfed0000,0x3f440000,0x3f44c000,0xbfed4000,
0x3f443fb5,0x3fedbfb5,0xbfed3fb5,0xbf443fb5,0xbfe20000,0xbf150000,0x3f71c000,0x3ff5c000,0x3e493fd5,0xbfc63f8e,0xbfff3f8e,0x3fa2bfd5,
0x3fc6bfed,0xbfff3fed,0x3fa23f44,0x3e49bf44,0xbff53ec8,0xbfe23ffb,0x3f15bffb,0xbf713ec8,0x3f8ec000,0x3ffbc000,0x3fd50000,0x3ec80000,
0xbffb3f44,0x3fd5bfed,0x3ec8bfed,0x3f8ebf44,0x3ec83fb5,0x3f8ebfb5,0xbffb3fb5,0x3fd5bfb5,0x3fd5bfed,0x3ec8bf44,0x3f8e3f44,0x3ffbbfed,
0x3fc60000,0x3e490000,0xbfa24000,0xbfff4000,0x3f71bffb,0x3f15bec8,0x3fe2bec8,0xbff53ffb,0xbff53f44,0x3f71bf44,0x3f15bfed,0xbfe23fed,
0xbe493fd5,0x3fa2bf8e,0xbfff3f8e,0xbfc63fd5,0xc0004000,0xbfb54000,0x0,0x3fb50000,0xc0004000,0x3fb50000,0x0,0x3fb5c000,
0xc0004000,0x3fb5c000,0x0,0xbfb50000,0xc0004000,0xbfb50000,0x0,0xbfb54000,0x3e490000,0x3fc60000,0x3fffc000,0x3fa2c000,
0x3f15bec8,0x3f71bffb,0x3ff5bffb,0xbfe23ec8,0x3f71bf44,0xbff53f44,0x3fe2bfed,0xbf153fed,0x3fa2bf8e,0xbe493fd5,0x3fc6bfd5,0x3fffbf8e,
0x3ffbc000,0x3f8ec000,0xbec80000,0xbfd50000,0x3fd5bfed,0xbffb3f44,0xbf8e3f44,0xbec83fed,0x3f8ebfb5,0x3ec83fb5,0xbfd53fb5,0x3ffbbfb5,
0x3ec8bf44,0x3fd5bfed,0xbffb3fed,0xbf8ebf44,0xbf150000,0xbfe20000,0xbff54000,0xbf714000,0xbfc63f8e,0x3e493fd5,0xbfa23fd5,0x3fffbf8e,
0xbfff3fed,0x3fc6bfed,0xbe493f44,0xbfa2bf44,0xbfe23ffb,0xbff53ec8,0x3f71bec8,0xbf153ffb,0xbfed4000,0xbf444000,0x3f440000,0x3fed0000,
0xbf443fb5,0x3fedbfb5,0x3fedbfb5,0xbf44bfb5,0x3f440000,0xbfed0000,0x3fedc000,0xbf444000,0x3fedbfb5,0x3f443fb5,0x3f44bfb5,0x3fedbfb5,
0x3f710000,0x3ff50000,0x3fe2c000,0x3f15c000,0x3fffbfd5,0xbfa2bf8e,0x3e49bf8e,0xbfc63fd5,0x3fa2bfed,0x3e493fed,0xbfc63f44,0x3fffbf44,
0xbf15bec8,0x3f71bffb,0xbff53ffb,0xbfe2bec8,0x3fd5c000,0x3ec8c000,0xbf8e0000,0xbffb0000,0xbec8bf44,0xbf8e3fed,0xbffb3fed,0x3fd53f44,
0xbffb3fb5,0x3fd5bfb5,0xbec83fb5,0xbf8ebfb5,0xbf8e3fed,0xbffb3f44,0x3fd5bf44,0x3ec83fed,0xbfa20000,0xbfff0000,0xbfc64000,0xbe494000,
0xbfe23ffb,0x3ff53ec8,0x3f713ec8,0x3f15bffb,0x3f153f44,0xbfe2bf44,0x3ff5bfed,0xbf713fed,0x3fffbfd5,0x3fc63f8e,0xbe49bf8e,0x3fa2bfd5,
0x4000,0x3fb54000,0x40000000,0x3fb50000,0xc000,0xbfb50000,0xc0000000,0x3fb54000,0x4000,0xbfb5c000,0x40000000,0xbfb50000,
0xc000,0x3fb50000,0xc0000000,0xbfb5c000,0x3fff0000,0x3fa20000,0xbe49c000,0xbfc6c000,0xbff53ec8,0x3fe23ffb,0x3f153ffb,0x3f71bec8,
0x3fe2bf44,0xbf153f44,0xbf71bfed,0x3ff53fed,0xbfc63f8e,0xbfffbfd5,0x3fa23fd5,0xbe493f8e,0xbec8c000,0xbfd5c000,0xbffb0000,0xbf8e0000,
0x3f8e3fed,0x3ec8bf44,0x3fd5bf44,0xbffbbfed,0xbfd5bfb5,0x3ffb3fb5,0xbf8e3fb5,0xbec8bfb5,0x3ffb3f44,0x3f8e3fed,0x3ec8bfed,0x3fd53f44,
0xbff50000,0xbf710000,0x3f154000,0x3fe24000,0x3fa2bf8e,0xbfffbfd5,0xbfc6bfd5,0x3e493f8e,0xbe493fed,0xbfa2bfed,0x3fff3f44,0xbfc6bf44,
0xbf71bffb,0x3f15bec8,0xbfe23ec8,0xbff5bffb,0x3f444000,0x3fed4000,0x3fed0000,0x3f440000,0xbfedbfb5,0x3f443fb5,0xbf443fb5,0x3fed3fb5,
0x3fed0000,0xbf440000,0xbf44c000,0x3fed4000,0xbf443fb5,0xbfedbfb5,0x3fed3fb5,0x3f443fb5,0x3fe20000,0x3f150000,0xbf71c000,0xbff5c000,
0xbe493fd5,0x3fc63f8e,0x3fff3f8e,0xbfa2bfd5,0xbfc6bfed,0x3fff3fed,0xbfa23f44,0xbe49bf44,0x3ff53ec8,0x3fe23ffb,0xbf15bffb,0x3f713ec8,
0xbf8ec000,0xbffbc000,0xbfd50000,0xbec80000,0x3ffb3f44,0xbfd5bfed,0xbec8bfed,0xbf8ebf44,0xbec83fb5,0xbf8ebfb5,0x3ffb3fb5,0xbfd5bfb5,
0xbfd5bfed,0xbec8bf44,0xbf8e3f44,0xbffbbfed,0xbfc60000,0xbe490000,0x3fa24000,0x3fff4000,0xbf71bffb,0xbf15bec8,0xbfe2bec8,0x3ff53ffb,
0x3ff53f44,0xbf71bf44,0xbf15bfed,0x3fe23fed,0x3e493fd5,0xbfa2bf8e,0x3fff3f8e,0x3fc63fd5,0x40004000,0x3fb54000,0x0,0xbfb50000,
0x40004000,0xbfb50000,0x0,0xbfb5c000,0x40004000,0xbfb5c000,0x0,0x3fb50000,0x40004000,0x3fb50000,0x0,0x3fb54000,
0xbfc6bfb5,0xbfffbfb5,0xbfa2bfb5,0x3e49bfb5,0xbfe2bfd5,0x3f15bf8e,0xbf71bf8e,0x3ff53fd5,0xbff5bfed,0x3fe23fed,0xbf15bf44,0xbf713f44,
0xbfffbffb,0xbfa23ec8,0xbe49bec8,0xbfc6bffb,0x3ec80000,0x3fd50000,0x3ffb4000,0x3f8e4000,0x3f8e3f44,0x3ec83fed,0x3fd53fed,0xbffbbf44,
0x3fd53fb5,0xbffbbfb5,0x3f8e3fb5,0x3ec8bfb5,0x3ffb3fed,0x3f8ebf44,0x3ec83f44,0x3fd53fed,0x3f713fb5,0xbf153fb5,0xbfe2bfb5,0xbff5bfb5,
0xbe493ec8,0xbfa2bffb,0xbfffbffb,0x3fc6bec8,0xbfa2bf44,0x3fff3f44,0xbfc6bfed,0x3e493fed,0xbff5bfd5,0xbf713f8e,0xbf15bf8e,0xbfe2bfd5,
0xbfedc000,0xbf44c000,0x3f440000,0x3fed0000,0xbf44bfb5,0x3fed3fb5,0x3fed3fb5,0xbf443fb5,0x3f440000,0xbfed0000,0x3fed4000,0xbf44c000,
0x3fed3fb5,0x3f44bfb5,0x3f443fb5,0x3fed3fb5,0x3ff53fb5,0x3fe23fb5,0x3f153fb5,0xbf713fb5,0x3fc63ffb,0xbfffbec8,0xbfa2bec8,0xbe49bffb,
0xbe493f44,0x3fc6bf44,0xbfffbfed,0x3fa23fed,0xbfe2bf8e,0xbf153fd5,0xbf71bfd5,0xbff5bf8e,0xbf8e0000,0xbffb0000,0xbfd5c000,0xbec8c000,
0xbffbbfed,0x3fd5bf44,0x3ec8bf44,0x3f8e3fed,0xbec8bfb5,0xbf8e3fb5,0x3ffb3fb5,0xbfd5bfb5,0x3fd53f44,0x3ec8bfed,0x3f8e3fed,0x3ffb3f44,
0xbe49bfb5,0x3fa2bfb5,0x3fff3fb5,0x3fc63fb5,0x3ff53f8e,0xbf713fd5,0x3f153fd5,0xbfe2bf8e,0x3f713fed,0x3f15bfed,0xbfe2bf44,0x3ff53f44,
0xbfc6bec8,0xbe493ffb,0xbfa2bffb,0xbfffbec8,0x4000,0xbfb54000,0xc0000000,0xbfb50000,0xc000,0x3fb50000,0x40000000,0xbfb54000,
0x4000,0x3fb5c000,0xc0000000,0x3fb50000,0xc000,0xbfb50000,0x40000000,0x3fb5c000,0xbfa2bfb5,0x3e49bfb5,0x3fc6bfb5,0x3fffbfb5,
0x3f713fd5,0xbff53f8e,0xbfe23f8e,0x3f15bfd5,0xbf15bfed,0xbf713fed,0x3ff5bf44,0xbfe23f44,0x3e493ffb,0x3fc6bec8,0xbfff3ec8,0xbfa23ffb,
0x3ffb0000,0x3f8e0000,0xbec84000,0xbfd54000,0xbfd5bf44,0x3ffbbfed,0x3f8ebfed,0x3ec83f44,0x3f8e3fb5,0x3ec8bfb5,0xbfd53fb5,0x3ffbbfb5,
0xbec8bfed,0xbfd53f44,0x3ffbbf44,0x3f8ebfed,0xbfe23fb5,0xbff53fb5,0xbf71bfb5,0x3f15bfb5,0x3fffbec8,0xbfc63ffb,0xbe493ffb,0xbfa23ec8,
0xbfc6bf44,0x3e493f44,0x3fa2bfed,0xbfff3fed,0x3f153fd5,0x3fe2bf8e,0xbff53f8e,0xbf713fd5,0x3f44c000,0x3fedc000,0x3fed0000,0x3f440000,
0xbfed3fb5,0x3f44bfb5,0xbf44bfb5,0x3fedbfb5,0x3fed0000,0xbf440000,0xbf444000,0x3fedc000,0xbf44bfb5,0xbfed3fb5,0x3fedbfb5,0x3f44bfb5,
0x3f153fb5,0xbf713fb5,0xbff53fb5,0xbfe23fb5,0x3fa2bffb,0x3e493ec8,0x3fc63ec8,0xbfff3ffb,0xbfff3f44,0x3fa2bf44,0x3e49bfed,0xbfc63fed,
0x3f713f8e,0x3ff5bfd5,0xbfe23fd5,0xbf153f8e,0xbfd50000,0xbec80000,0x3f8ec000,0x3ffbc000,0xbec83fed,0xbf8e3f44,0xbffb3f44,0x3fd5bfed,
0x3ffbbfb5,0xbfd53fb5,0x3ec83fb5,0x3f8ebfb5,0xbf8ebf44,0xbffb3fed,0x3fd5bfed,0x3ec8bf44,0x3fffbfb5,0x3fc6bfb5,0x3e493fb5,0xbfa23fb5,
0xbf15bf8e,0x3fe2bfd5,0x3ff5bfd5,0xbf713f8e,0xbfe23fed,0x3ff5bfed,0xbf71bf44,0xbf153f44,0x3fa23ec8,0x3fffbffb,0xbfc63ffb,0xbe493ec8,
0xc0004000,0xbfb54000,0x0,0x3fb50000,0xc0004000,0x3fb50000,0x0,0x3fb5c000,0xc0004000,0x3fb5c000,0x0,0xbfb50000,
0xc0004000,0xbfb50000,0x0,0xbfb54000,0x3fc6bfb5,0x3fffbfb5,0x3fa2bfb5,0xbe49bfb5,0x3fe2bfd5,0xbf15bf8e,0x3f71bf8e,0xbff53fd5,
0x3ff5bfed,0xbfe23fed,0x3f15bf44,0x3f713f44,0x3fffbffb,0x3fa23ec8,0x3e49bec8,0x3fc6bffb,0xbec80000,0xbfd50000,0xbffb4000,0xbf8e4000,
0xbf8e3f44,0xbec83fed,0xbfd53fed,0x3ffbbf44,0xbfd53fb5,0x3ffbbfb5,0xbf8e3fb5,0xbec8bfb5,0xbffb3fed,0xbf8ebf44,0xbec83f44,0xbfd53fed,
0xbf713fb5,0x3f153fb5,0x3fe2bfb5,0x3ff5bfb5,0x3e493ec8,0x3fa2bffb,0x3fffbffb,0xbfc6bec8,0x3fa2bf44,0xbfff3f44,0x3fc6bfed,0xbe493fed,
0x3ff5bfd5,0x3f713f8e,0x3f15bf8e,0x3fe2bfd5,0x3fedc000,0x3f44c000,0xbf440000,0xbfed0000,0x3f44bfb5,0xbfed3fb5,0xbfed3fb5,0x3f443fb5,
0xbf440000,0x3fed0000,0xbfed4000,0x3f44c000,0xbfed3fb5,0xbf44bfb5,0xbf443fb5,0xbfed3fb5,0xbff53fb5,0xbfe23fb5,0xbf153fb5,0x3f713fb5,
0xbfc63ffb,0x3fffbec8,0x3fa2bec8,0x3e49bffb,0x3e493f44,0xbfc6bf44,0x3fffbfed,0xbfa23fed,0x3fe2bf8e,0x3f153fd5,0x3f71bfd5,0x3ff5bf8e,
0x3f8e0000,0x3ffb0000,0x3fd5c000,0x3ec8c000,0x3ffbbfed,0xbfd5bf44,0xbec8bf44,0xbf8e3fed,0x3ec8bfb5,0x3f8e3fb5,0xbffb3fb5,0x3fd5bfb5,
0xbfd53f44,0xbec8bfed,0xbf8e3fed,0xbffb3f44,0x3e49bfb5,0xbfa2bfb5,0xbfff3fb5,0xbfc63fb5,0xbff53f8e,0x3f713fd5,0xbf153fd5,0x3fe2bf8e,
0xbf713fed,0xbf15bfed,0x3fe2bf44,0xbff53f44,0x3fc6bec8,0x3e493ffb,0x3fa2bffb,0x3fffbec8,0x4000,0x3fb54000,0x40000000,0x3fb50000,
0xc000,0xbfb50000,0xc0000000,0x3fb54000,0x4000,0xbfb5c000,0x40000000,0xbfb50000,0xc000,0x3fb50000,0xc0000000,0xbfb5c000,
0x3fa2bfb5,0xbe49bfb5,0xbfc6bfb5,0xbfffbfb5,0xbf713fd5,0x3ff53f8e,0x3fe23f8e,0xbf15bfd5,0x3f15bfed,0x3f713fed,0xbff5bf44,0x3fe23f44,
0xbe493ffb,0xbfc6bec8,0x3fff3ec8,0x3fa23ffb,0xbffb0000,0xbf8e0000,0x3ec84000,0x3fd54000,0x3fd5bf44,0xbffbbfed,0xbf8ebfed,0xbec83f44,
0xbf8e3fb5,0xbec8bfb5,0x3fd53fb5,0xbffbbfb5,0x3ec8bfed,0x3fd53f44,0xbffbbf44,0xbf8ebfed,0x3fe23fb5,0x3ff53fb5,0x3f71bfb5,0xbf15bfb5,
0xbfffbec8,0x3fc63ffb,0x3e493ffb,0x3fa23ec8,0x3fc6bf44,0xbe493f44,0xbfa2bfed,0x3fff3fed,0xbf153fd5,0xbfe2bf8e,0x3ff53f8e,0x3f713fd5,
0xbf44c000,0xbfedc000,0xbfed0000,0xbf440000,0x3fed3fb5,0xbf44bfb5,0x3f44bfb5,0xbfedbfb5,0xbfed0000,0x3f440000,0x3f444000,0xbfedc000,
0x3f44bfb5,0x3fed3fb5,0xbfedbfb5,0xbf44bfb5,0xbf153fb5,0x3f713fb5,0x3ff53fb5,0x3fe23fb5,0xbfa2bffb,0xbe493ec8,0xbfc63ec8,0x3fff3ffb,
0x3fff3f44,0xbfa2bf44,0xbe49bfed,0x3fc63fed,0xbf713f8e,0xbff5bfd5,0x3fe23fd5,0x3f153f8e,0x3fd50000,0x3ec80000,0xbf8ec000,0xbffbc000,
0x3ec83fed,0x3f8e3f44,0x3ffb3f44,0xbfd5bfed,0xbffbbfb5,0x3fd53fb5,0xbec83fb5,0xbf8ebfb5,0x3f8ebf44,0x3ffb3fed,0xbfd5bfed,0xbec8bf44,
0xbfffbfb5,0xbfc6bfb5,0xbe493fb5,0x3fa23fb5,0x3f15bf8e,0xbfe2bfd5,0xbff5bfd5,0x3f713f8e,0x3fe23fed,0xbff5bfed,0x3f71bf44,0x3f153f44,
0xbfa23ec8,0xbfffbffb,0x3fc63ffb,0x3e493ec8,0x80003f80,0x3f800000,0x80003f80,0x3f800000,0x80003f80,0x3f800000,0x80003f80,0x3f800000,
0x80003f80,0x3f800000,0x80003f80,0x3f800000,0x80003f80,0x3f800000,0x80003f80,0x3f800000,0x80003f80,0x3f800000,0x8000bf80,0xbf800000,
0x3f353f35,0x3f35bf35,0xbf35bf35,0xbf353f35,0x3f800000,0xbf80,0xbf800000,0x3f80,0x3f35bf35,0xbf35bf35,0xbf353f35,0x3f353f35,
0x80003f80,0x3f800000,0x80003f80,0x3f800000,0x3f800000,0xbf80,0x3f800000,0xbf80,0x8000bf80,0xbf800000,0x8000bf80,0xbf800000,
0xbf800000,0x3f80,0xbf800000,0x3f80,0x80003f80,0x3f800000,0x8000bf80,0xbf800000,0x3f35bf35,0xbf35bf35,0xbf353f35,0x3f353f35,
0xbf800000,0x3f80,0x3f800000,0xbf80,0x3f353f35,0x3f35bf35,0xbf35bf35,0xbf353f35,0x80003f80,0x3f800000,0x80003f80,0x3f800000,
0x8000bf80,0xbf800000,0x8000bf80,0xbf800000,0x80003f80,0x3f800000,0x80003f80,0x3f800000,0x8000bf80,0xbf800000,0x8000bf80,0xbf800000,
0x80003f80,0x3f800000,0x8000bf80,0xbf800000,0xbf35bf35,0xbf353f35,0x3f353f35,0x3f35bf35,0x3f800000,0xbf80,0xbf800000,0x3f80,
0xbf353f35,0x3f353f35,0x3f35bf35,0xbf35bf35,0x80003f80,0x3f800000,0x80003f80,0x3f800000,0xbf800000,0x3f80,0xbf800000,0x3f80,
0x8000bf80,0xbf800000,0x8000bf80,0xbf800000,0x3f800000,0xbf80,0x3f800000,0xbf80,0x80003f80,0x3f800000,0x8000bf80,0xbf800000,
0xbf353f35,0x3f353f35,0x3f35bf35,0xbf35bf35,0xbf800000,0x3f80,0x3f800000,0xbf80,0xbf35bf35,0xbf353f35,0x3f353f35,0x3f35bf35,
0x3f803f80,0x80008000,0x80008000,0xbf80bf80,0x3f803f80,0x80008000,0x80008000,0xbf80bf80,0x3f803f80,0x80008000,0x80008000,0xbf80bf80,
0x3f803f80,0x80008000,0x80008000,0xbf80bf80,0x3f353f80,0x3f358000,0x3f358000,0xbf35bf80,0xbf350000,0x3f353f80,0x3f353f80,0x3f358000,
0xbf35bf80,0xbf358000,0xbf358000,0x3f353f80,0x3f350000,0xbf35bf80,0xbf35bf80,0xbf358000,0x3f80,0x3f808000,0x3f808000,0x8000bf80,
0xbf80,0xbf808000,0xbf808000,0x80003f80,0x3f80,0x3f808000,0x3f808000,0x8000bf80,0xbf80,0xbf808000,0xbf808000,0x80003f80,
0xbf353f80,0x3f358000,0x3f358000,0x3f35bf80,0x3f350000,0x3f35bf80,0x3f35bf80,0xbf358000,0x3f35bf80,0xbf358000,0xbf358000,0xbf353f80,
0xbf350000,0xbf353f80,0xbf353f80,0x3f358000,0xbf803f80,0x80008000,0x80008000,0x3f80bf80,0xbf803f80,0x80008000,0x80008000,0x3f80bf80,
0xbf803f80,0x80008000,0x80008000,0x3f80bf80,0xbf803f80,0x80008000,0x80008000,0x3f80bf80,0xbf353f80,0xbf358000,0xbf358000,0x3f35bf80,
0x3f350000,0xbf353f80,0xbf353f80,0xbf358000,0x3f35bf80,0x3f358000,0x3f358000,0xbf353f80,0xbf350000,0x3f35bf80,0x3f35bf80,0x3f358000,
0x3f80,0xbf808000,0xbf808000,0x8000bf80,0xbf80,0x3f808000,0x3f808000,0x80003f80,0x3f80,0xbf808000,0xbf808000,0x8000bf80,
0xbf80,0x3f808000,0x3f808000,0x80003f80,0x3f353f80,0xbf358000,0xbf358000,0xbf35bf80,0xbf350000,0xbf35bf80,0xbf35bf80,0x3f358000,
0xbf35bf80,0x3f358000,0x3f358000,0x3f353f80,0x3f350000,0x3f353f80,0x3f353f80,0xbf358000,0x3f800000,0x0,0x3f800000,0x0,
0x3f800000,0x0,0x3f800000,0x0,0x3f800000,0x0,0x3f800000,0x0,0x3f800000,0x0,0x3f800000,0x0,
0x3f800000,0x0,0x3f7fb10f,0xbd48fb30,0x3f7ec46d,0xbdc8bd36,0x3f7d3aac,0xbe164083,0x3f7b14be,0xbe47c5c2,0x3f7853f8,0xbe78cfcc,
0x3f74fa0b,0xbe94a031,0x3f710908,0xbeac7cd4,0x3f800000,0x0,0x3f7ec46d,0xbdc8bd36,0x3f7b14be,0xbe47c5c2,0x3f74fa0b,0xbe94a031,
0x3f6c835e,0xbec3ef15,0x3f61c598,0xbef15aea,0x3f54db31,0xbf0e39da,0x3f45e403,0xbf226799,0x3f800000,0x0,0x3f7d3aac,0xbe164083,
0x3f74fa0b,0xbe94a031,0x3f676bd8,0xbedae880,0x3f54db31,0xbf0e39da,0x3f3daef9,0xbf2beb4a,0x3f226799,0xbf45e403,0x3f039c3d,0xbf5b941a,
0x3f800000,0x0,0x3f7b14be,0xbe47c5c2,0x3f6c835e,0xbec3ef15,0x3f54db31,0xbf0e39da,0x3f3504f3,0xbf3504f3,0x3f0e39da,0xbf54db31,
0x3ec3ef15,0xbf6c835e,0x3e47c5c2,0xbf7b14be,0x3f800000,0x0,0x3f7853f8,0xbe78cfcc,0x3f61c598,0xbef15aea,0x3f3daef9,0xbf2beb4a,
0x3f0e39da,0xbf54db31,0x3eac7cd4,0xbf710908,0x3dc8bd36,0xbf7ec46d,0xbe164083,0xbf7d3aac,0x3f800000,0x0,0x3f74fa0b,0xbe94a031,
0x3f54db31,0xbf0e39da,0x3f226799,0xbf45e403,0x3ec3ef15,0xbf6c835e,0x3dc8bd36,0xbf7ec46d,0xbe47c5c2,0xbf7b14be,0xbef15aea,0xbf61c598,
0x3f800000,0x0,0x3f710908,0xbeac7cd4,0x3f45e403,0xbf226799,0x3f039c3d,0xbf5b941a,0x3e47c5c2,0xbf7b14be,0xbe164083,0xbf7d3aac,
0xbef15aea,0xbf61c598,0xbf3daef9,0xbf2beb4a,0x3f800000,0x0,0x3f800000,0x0,0x3f800000,0x0,0x3f800000,0x0,
0x3f800000,0x0,0x3f800000,0x0,0x3f800000,0x0,0x3f800000,0x0,0x3f6c835e,0xbec3ef15,0x3f676bd8,0xbedae880,
0x3f61c598,0xbef15aea,0x3f5b941a,0xbf039c3d,0x3f54db31,0xbf0e39da,0x3f4d9f02,0xbf187fc0,0x3f45e403,0xbf226799,0x3f3daef9,0xbf2beb4a,
0x3f3504f3,0xbf3504f3,0x3f226799,0xbf45e403,0x3f0e39da,0xbf54db31,0x3ef15aea,0xbf61c598,0x3ec3ef15,0xbf6c835e,0x3e94a031,0xbf74fa0b,
0x3e47c5c2,0xbf7b14be,0x3dc8bd36,0xbf7ec46d,0x3ec3ef15,0xbf6c835e,0x3e78cfcc,0xbf7853f8,0x3dc8bd36,0xbf7ec46d,0xbd48fb30,0xbf7fb10f,
0xbe47c5c2,0xbf7b14be,0xbeac7cd4,0xbf710908,0xbef15aea,0xbf61c598,0xbf187fc0,0xbf4d9f02,0x0,0xbf800000,0xbe47c5c2,0xbf7b14be,
0xbec3ef15,0xbf6c835e,0xbf0e39da,0xbf54db31,0xbf3504f3,0xbf3504f3,0xbf54db31,0xbf0e39da,0xbf6c835e,0xbec3ef15,0xbf7b14be,0xbe47c5c2,
0xbec3ef15,0xbf6c835e,0xbf187fc0,0xbf4d9f02,0xbf45e403,0xbf226799,0xbf676bd8,0xbedae880,0xbf7b14be,0xbe47c5c2,0xbf7fb10f,0x3d48fb30,
0xbf74fa0b,0x3e94a031,0xbf5b941a,0x3f039c3d,0xbf3504f3,0xbf3504f3,0xbf61c598,0xbef15aea,0xbf7b14be,0xbe47c5c2,0xbf7ec46d,0x3dc8bd36,
0xbf6c835e,0x3ec3ef15,0xbf45e403,0x3f226799,0xbf0e39da,0x3f54db31,0xbe94a031,0x3f74fa0b,0xbf6c835e,0xbec3ef15,0xbf7fb10f,0xbd48fb30,
0xbf74fa0b,0x3e94a031,0xbf4d9f02,0x3f187fc0,0xbf0e39da,0x3f54db31,0xbe78cfcc,0x3f7853f8,0x3dc8bd36,0x3f7ec46d,0x3edae880,0x3f676bd8,
0x80003f80,0x3f800000,0x3f800000,0xbf80,0x3ec43f6d,0x3f6dbec4,0x3f6dbec4,0xbec4bf6d,0x3f353f35,0x3f35bf35,0x3f35bf35,0xbf35bf35,
0x3f6d3ec4,0x3ec4bf6d,0x3ec4bf6d,0xbf6dbec4,0x80003f80,0x3f800000,0xbf800000,0x3f80,0x3f6d3ec4,0x3ec4bf6d,0xbec43f6d,0x3f6d3ec4,
0x3f35bf35,0xbf35bf35,0x3f353f35,0x3f35bf35,0xbec4bf6d,0xbf6d3ec4,0x3f6dbec4,0xbec4bf6d,0x80003f80,0x3f800000,0x3f800000,0xbf80,
0x3f6dbec4,0xbec4bf6d,0xbec4bf6d,0xbf6d3ec4,0xbf35bf35,0xbf353f35,0xbf353f35,0x3f353f35,0xbec43f6d,0x3f6d3ec4,0x3f6d3ec4,0x3ec4bf6d,
0x80003f80,0x3f800000,0xbf800000,0x3f80,0x3ec4bf6d,0xbf6dbec4,0x3f6d3ec4,0x3ec4bf6d,0xbf353f35,0x3f353f35,0xbf35bf35,0xbf353f35,
0x3f6dbec4,0xbec4bf6d,0x3ec43f6d,0x3f6dbec4,0x80003f80,0x3f800000,0x3f800000,0xbf80,0xbec4bf6d,0xbf6d3ec4,0xbf6d3ec4,0x3ec43f6d,
0x3f353f35,0x3f35bf35,0x3f35bf35,0xbf35bf35,0xbf6dbec4,0xbec43f6d,0xbec43f6d,0x3f6d3ec4,0x80003f80,0x3f800000,0xbf800000,0x3f80,
0xbf6dbec4,0xbec43f6d,0x3ec4bf6d,0xbf6dbec4,0x3f35bf35,0xbf35bf35,0x3f353f35,0x3f35bf35,0x3ec43f6d,0x3f6dbec4,0xbf6d3ec4,0x3ec43f6d,
0x80003f80,0x3f800000,0x3f800000,0xbf80,0xbf6d3ec4,0x3ec43f6d,0x3ec43f6d,0x3f6dbec4,0xbf35bf35,0xbf353f35,0xbf353f35,0x3f353f35,
0x3ec4bf6d,0xbf6dbec4,0xbf6dbec4,0xbec43f6d,0x80003f80,0x3f800000,0xbf800000,0x3f80,0xbec43f6d,0x3f6d3ec4,0xbf6dbec4,0xbec43f6d,
0xbf353f35,0x3f353f35,0xbf35bf35,0xbf353f35,0xbf6d3ec4,0x3ec43f6d,0xbec4bf6d,0xbf6d3ec4,0x3f803f80,0x80008000,0x80008000,0xbf80bf80,
0x3f803f80,0x80008000,0x80008000,0xbf80bf80,0x3f803f80,0x80008000,0x80008000,0xbf80bf80,0x3f803f80,0x80008000,0x80008000,0xbf80bf80,
0x3ec43f6d,0x3f6d3ec4,0x3f6d3ec4,0xbec4bf6d,0xbf6dbec4,0x3ec43f6d,0x3ec43f6d,0x3f6d3ec4,0xbec4bf6d,0xbf6dbec4,0xbf6dbec4,0x3ec43f6d,
0x3f6d3ec4,0xbec4bf6d,0xbec4bf6d,0xbf6dbec4,0xbf353f35,0x3f353f35,0x3f353f35,0x3f35bf35,0x3f35bf35,0xbf35bf35,0xbf35bf35,0xbf353f35,
0xbf353f35,0x3f353f35,0x3f353f35,0x3f35bf35,0x3f35bf35,0xbf35bf35,0xbf35bf35,0xbf353f35,0xbf6d3ec4,0xbec43f6d,0xbec43f6d,0x3f6dbec4,
0xbec43f6d,0x3f6dbec4,0x3f6dbec4,0x3ec4bf6d,0x3f6dbec4,0x3ec4bf6d,0x3ec4bf6d,0xbf6d3ec4,0x3ec4bf6d,0xbf6d3ec4,0xbf6d3ec4,0xbec43f6d,
0x0,0xbf803f80,0xbf803f80,0x80008000,0x0,0xbf803f80,0xbf803f80,0x80008000,0x0,0xbf803f80,0xbf803f80,0x80008000,
0x0,0xbf803f80,0xbf803f80,0x80008000,0x3f6dbec4,0xbec43f6d,0xbec43f6d,0xbf6d3ec4,0x3ec4bf6d,0x3f6dbec4,0x3f6dbec4,0xbec43f6d,
0xbf6d3ec4,0x3ec4bf6d,0x3ec4bf6d,0x3f6dbec4,0xbec43f6d,0xbf6d3ec4,0xbf6d3ec4,0x3ec4bf6d,0x3f35bf35,0x3f353f35,0x3f353f35,0xbf353f35,
0xbf353f35,0xbf35bf35,0xbf35bf35,0x3f35bf35,0x3f35bf35,0x3f353f35,0x3f353f35,0xbf353f35,0xbf353f35,0xbf35bf35,0xbf35bf35,0x3f35bf35,
0xbec4bf6d,0x3f6d3ec4,0x3f6d3ec4,0x3ec43f6d,0x3f6d3ec4,0x3ec43f6d,0x3ec43f6d,0xbf6dbec4,0x3ec43f6d,0xbf6dbec4,0xbf6dbec4,0xbec4bf6d,
0xbf6dbec4,0xbec4bf6d,0xbec4bf6d,0x3f6d3ec4,0x3f800000,0x0,0x3f7fec43,0xbcc90ab0,0x3f7fb10f,0xbd48fb30,0x3f7f4e6d,0xbd96a905,
0x3f7ec46d,0xbdc8bd36,0x3f7e1324,0xbdfab273,0x3f7d3aac,0xbe164083,0x3f7c3b28,0xbe2f10a2,0x3f800000,0x0,0x3f7f4e6d,0xbd96a905,
0x3f7d3aac,0xbe164083,0x3f79c79d,0xbe605c13,0x3f74fa0b,0xbe94a031,0x3f6ed89e,0xbeb8442a,0x3f676bd8,0xbedae880,0x3f5ebe05,0xbefc5d27,
0x3f800000,0x0,0x3f7e1324,0xbdfab273,0x3f7853f8,0xbe78cfcc,0x3f6ed89e,0xbeb8442a,0x3f61c598,0xbef15aea,0x3f514d3d,0xbf13682a,
0x3f3daef9,0xbf2beb4a,0x3f273656,0xbf41d870,0x3f800000,0x0,0x3f7c3b28,0xbe2f10a2,0x3f710908,0xbeac7cd4,0x3f5ebe05,0xbefc5d27,
0x3f45e403,0xbf226799,0x3f273656,0xbf41d870,0x3f039c3d,0xbf5b941a,0x3eb8442a,0xbf6ed89e,0x3f800000,0x0,0x3f79c79d,0xbe605c13,
0x3f676bd8,0xbedae880,0x3f49d112,0xbf1d7fd1,0x3f226799,0xbf45e403,0x3ee63375,0xbf64aa59,0x3e78cfcc,0xbf7853f8,0x3cc90ab0,0xbf7fec43,
0x3f800000,0x0,0x3f76ba07,0xbe888e93,0x3f5b941a,0xbf039c3d,0x3f3085bb,0xbf396842,0x3ef15aea,0xbf61c598,0x3e605c13,0xbf79c79d,
0xbd48fb30,0xbf7fb10f,0xbea09ae5,0xbf731447,0x3f800000,0x0,0x3f731447,0xbea09ae5,0x3f4d9f02,0xbf187fc0,0x3f13682a,0xbf514d3d,
0x3e94a031,0xbf74fa0b,0xbcc90ab0,0xbf7fec43,0xbeac7cd4,0xbf710908,0xbf1d7fd1,0xbf49d112,0x3f800000,0x0,0x3f6ed89e,0xbeb8442a,
0x3f3daef9,0xbf2beb4a,0x3ee63375,0xbf64aa59,0x3dc8bd36,0xbf7ec46d,0xbe888e93,0xbf76ba07,0xbf187fc0,0xbf4d9f02,0xbf584853,0xbf08f59b,
0x3f7b14be,0xbe47c5c2,0x3f79c79d,0xbe605c13,0x3f7853f8,0xbe78cfcc,0x3f76ba07,0xbe888e93,0x3f74fa0b,0xbe94a031,0x3f731447,0xbea09ae5,
0x3f710908,0xbeac7cd4,0x3f6ed89e,0xbeb8442a,0x3f54db31,0xbf0e39da,0x3f49d112,0xbf1d7fd1,0x3f3daef9,0xbf2beb4a,0x3f3085bb,0xbf396842,
0x3f226799,0xbf45e403,0x3f13682a,0xbf514d3d,0x3f039c3d,0xbf5b941a,0x3ee63375,0xbf64aa59,0x3f0e39da,0xbf54db31,0x3ee63375,0xbf64aa59,
0x3eac7cd4,0xbf710908,0x3e605c13,0xbf79c79d,0x3dc8bd36,0xbf7ec46d,0xbcc90ab0,0xbf7fec43,0xbe164083,0xbf7d3aac,0xbe888e93,0xbf76ba07,
0x3e47c5c2,0xbf7b14be,0x3cc90ab0,0xbf7fec43,0xbe164083,0xbf7d3aac,0xbea09ae5,0xbf731447,0xbef15aea,0xbf61c598,0xbf1d7fd1,0xbf49d112,
0xbf3daef9,0xbf2beb4a,0xbf584853,0xbf08f59b,0xbe47c5c2,0xbf7b14be,0xbecf7bca,0xbf6a09a7,0xbf187fc0,0xbf4d9f02,0xbf41d870,0xbf273656,
0xbf61c598,0xbef15aea,0xbf76ba07,0xbe888e93,0xbf7fb10f,0xbd48fb30,0xbf7c3b28,0x3e2f10a2,0xbf0e39da,0xbf54db31,0xbf41d870,0xbf273656,
0xbf676bd8,0xbedae880,0xbf7c3b28,0xbe2f10a2,0xbf7ec46d,0x3dc8bd36,0xbf6ed89e,0x3eb8442a,0xbf4d9f02,0x3f187fc0,0xbf1d7fd1,0x3f49d112,
0xbf54db31,0xbf0e39da,0xbf76ba07,0xbe888e93,0xbf7fb10f,0x3d48fb30,0xbf6ed89e,0x3eb8442a,0xbf45e403,0x3f226799,0xbf08f59b,0x3f584853,
0xbe78cfcc,0x3f7853f8,0x3d96a905,0x3f7f4e6d,0xbf7b14be,0xbe47c5c2,0xbf7c3b28,0x3e2f10a2,0xbf5b941a,0x3f039c3d,0xbf1d7fd1,0x3f49d112,
0xbe94a031,0x3f74fa0b,0x3d96a905,0x3f7f4e6d,0x3edae880,0x3f676bd8,0x3f396842,0x3f3085bb,0x80003f80,0x80003f80,0x80003f80,0x80003f80,
0x80003f80,0x80003f80,0x80003f80,0x80003f80,0x80003f80,0x80003f80,0x80003f80,0x80003f80,0x80003f80,0x80003f80,0x80003f80,0x80003f80,
0x3f800000,0x3f800000,0x3f800000,0x3f800000,0x3f800000,0x3f800000,0x3f800000,0x3f800000,0x3f800000,0x3f800000,0x3f800000,0x3f800000,
0x3f800000,0x3f800000,0x3f800000,0x3f800000,0x80003f80,0x3f353f35,0x80003f80,0x3f353f35,0x3f800000,0x3f35bf35,0x3f800000,0x3f35bf35,
0x8000bf80,0xbf35bf35,0x8000bf80,0xbf35bf35,0xbf800000,0xbf353f35,0xbf800000,0xbf353f35,0x3f800000,0x3f35bf35,0x3f800000,0x3f35bf35,
0xbf80,0xbf35bf35,0xbf80,0xbf35bf35,0xbf800000,0xbf353f35,0xbf800000,0xbf353f35,0x3f80,0x3f353f35,0x3f80,0x3f353f35,
0x80003f80,0x3f800000,0x80003f80,0x3f800000,0x8000bf80,0xbf800000,0x8000bf80,0xbf800000,0x80003f80,0x3f800000,0x80003f80,0x3f800000,
0x8000bf80,0xbf800000,0x8000bf80,0xbf800000,0x3f800000,0xbf80,0x3f800000,0xbf80,0xbf800000,0x3f80,0xbf800000,0x3f80,
0x3f800000,0xbf80,0x3f800000,0xbf80,0xbf800000,0x3f80,0xbf800000,0x3f80,0x80003f80,0x3f35bf35,0x80003f80,0x3f35bf35,
0xbf800000,0x3f353f35,0xbf800000,0x3f353f35,0x8000bf80,0xbf353f35,0x8000bf80,0xbf353f35,0x3f800000,0xbf35bf35,0x3f800000,0xbf35bf35,
0x3f800000,0xbf35bf35,0x3f800000,0xbf35bf35,0x3f80,0x3f35bf35,0x3f80,0x3f35bf35,0xbf800000,0x3f353f35,0xbf800000,0x3f353f35,
0xbf80,0xbf353f35,0xbf80,0xbf353f35,0x80003f80,0x3ec43f6d,0x8000bf80,0xbec4bf6d,0x3f353f35,0x3f6d3ec4,0xbf35bf35,0xbf6dbec4,
0x3f800000,0x3f6dbec4,0xbf800000,0xbf6d3ec4,0x3f35bf35,0x3ec4bf6d,0xbf353f35,0xbec43f6d,0x3f800000,0x3f6dbec4,0xbf800000,0xbf6d3ec4,
0x3f35bf35,0x3ec4bf6d,0xbf353f35,0xbec43f6d,0xbf80,0xbec4bf6d,0x3f80,0x3ec43f6d,0xbf35bf35,0xbf6dbec4,0x3f353f35,0x3f6d3ec4,
0x80003f80,0x3f6d3ec4,0x8000bf80,0xbf6dbec4,0x3f35bf35,0xbec4bf6d,0xbf353f35,0x3ec43f6d,0xbf800000,0xbec43f6d,0x3f800000,0x3ec4bf6d,
0x3f353f35,0x3f6dbec4,0xbf35bf35,0xbf6d3ec4,0x3f800000,0x3ec4bf6d,0xbf800000,0xbec43f6d,0xbf35bf35,0xbf6d3ec4,0x3f353f35,0x3f6dbec4,
0x3f80,0x3f6d3ec4,0xbf80,0xbf6dbec4,0x3f35bf35,0xbec4bf6d,0xbf353f35,0x3ec43f6d,0x80003f80,0x3f6dbec4,0x8000bf80,0xbf6d3ec4,
0xbf35bf35,0xbec43f6d,0x3f353f35,0x3ec4bf6d,0x3f800000,0xbec4bf6d,0xbf800000,0x3ec43f6d,0xbf353f35,0x3f6d3ec4,0x3f35bf35,0xbf6dbec4,
0x3f800000,0xbec4bf6d,0xbf800000,0x3ec43f6d,0xbf353f35,0x3f6d3ec4,0x3f35bf35,0xbf6dbec4,0xbf80,0xbf6d3ec4,0x3f80,0x3f6dbec4,
0x3f353f35,0x3ec4bf6d,0xbf35bf35,0xbec43f6d,0x80003f80,0x3ec4bf6d,0x8000bf80,0xbec43f6d,0xbf353f35,0x3f6dbec4,0x3f35bf35,0xbf6d3ec4,
0xbf800000,0x3f6d3ec4,0x3f800000,0xbf6dbec4,0xbf35bf35,0x3ec43f6d,0x3f353f35,0xbec4bf6d,0x3f800000,0xbf6dbec4,0xbf800000,0x3f6d3ec4,
0x3f353f35,0xbec4bf6d,0xbf35bf35,0x3ec43f6d,0x3f80,0x3ec4bf6d,0xbf80,0xbec43f6d,0xbf353f35,0x3f6dbec4,0x3f35bf35,0xbf6d3ec4,
0x80003f80,0x8000bf80,0x80003f80,0x8000bf80,0x80003f80,0x8000bf80,0x80003f80,0x8000bf80,0x80003f80,0x8000bf80,0x80003f80,0x8000bf80,
0x80003f80,0x8000bf80,0x80003f80,0x8000bf80,0x3f800000,0xbf800000,0x3f800000,0xbf800000,0x3f800000,0xbf800000,0x3f800000,0xbf800000,
0x3f800000,0xbf800000,0x3f800000,0xbf800000,0x3f800000,0xbf800000,0x3f800000,0xbf800000,0x80003f80,0xbf35bf35,0x80003f80,0xbf35bf35,
0x3f800000,0xbf353f35,0x3f800000,0xbf353f35,0x8000bf80,0x3f353f35,0x8000bf80,0x3f353f35,0xbf800000,0x3f35bf35,0xbf800000,0x3f35bf35,
0x3f800000,0xbf353f35,0x3f800000,0xbf353f35,0xbf80,0x3f353f35,0xbf80,0x3f353f35,0xbf800000,0x3f35bf35,0xbf800000,0x3f35bf35,
0x3f80,0xbf35bf35,0x3f80,0xbf35bf35,0x80003f80,0xbf800000,0x80003f80,0xbf800000,0x8000bf80,0x3f800000,0x8000bf80,0x3f800000,
0x80003f80,0xbf800000,0x80003f80,0xbf800000,0x8000bf80,0x3f800000,0x8000bf80,0x3f800000,0x3f800000,0x3f80,0x3f800000,0x3f80,
0xbf800000,0xbf80,0xbf800000,0xbf80,0x3f800000,0x3f80,0x3f800000,0x3f80,0xbf800000,0xbf80,0xbf800000,0xbf80,
0x80003f80,0xbf353f35,0x80003f80,0xbf353f35,0xbf800000,0xbf35bf35,0xbf800000,0xbf35bf35,0x8000bf80,0x3f35bf35,0x8000bf80,0x3f35bf35,
0x3f800000,0x3f353f35,0x3f800000,0x3f353f35,0x3f800000,0x3f353f35,0x3f800000,0x3f353f35,0x3f80,0xbf353f35,0x3f80,0xbf353f35,
0xbf800000,0xbf35bf35,0xbf800000,0xbf35bf35,0xbf80,0x3f35bf35,0xbf80,0x3f35bf35,0x80003f80,0xbec4bf6d,0x8000bf80,0x3ec43f6d,
0x3f353f35,0xbf6dbec4,0xbf35bf35,0x3f6d3ec4,0x3f800000,0xbf6d3ec4,0xbf800000,0x3f6dbec4,0x3f35bf35,0xbec43f6d,0xbf353f35,0x3ec4bf6d,
0x3f800000,0xbf6d3ec4,0xbf800000,0x3f6dbec4,0x3f35bf35,0xbec43f6d,0xbf353f35,0x3ec4bf6d,0xbf80,0x3ec43f6d,0x3f80,0xbec4bf6d,
0xbf35bf35,0x3f6d3ec4,0x3f353f35,0xbf6dbec4,0x80003f80,0xbf6dbec4,0x8000bf80,0x3f6d3ec4,0x3f35bf35,0x3ec43f6d,0xbf353f35,0xbec4bf6d,
0xbf800000,0x3ec4bf6d,0x3f800000,0xbec43f6d,0x3f353f35,0xbf6d3ec4,0xbf35bf35,0x3f6dbec4,0x3f800000,0xbec43f6d,0xbf800000,0x3ec4bf6d,
0xbf35bf35,0x3f6dbec4,0x3f353f35,0xbf6d3ec4,0x3f80,0xbf6dbec4,0xbf80,0x3f6d3ec4,0x3f35bf35,0x3ec43f6d,0xbf353f35,0xbec4bf6d,
0x80003f80,0xbf6d3ec4,0x8000bf80,0x3f6dbec4,0xbf35bf35,0x3ec4bf6d,0x3f353f35,0xbec43f6d,0x3f800000,0x3ec43f6d,0xbf800000,0xbec4bf6d,
0xbf353f35,0xbf6dbec4,0x3f35bf35,0x3f6d3ec4,0x3f800000,0x3ec43f6d,0xbf800000,0xbec4bf6d,0xbf353f35,0xbf6dbec4,0x3f35bf35,0x3f6d3ec4,
0xbf80,0x3f6dbec4,0x3f80,0xbf6d3ec4,0x3f353f35,0xbec43f6d,0xbf35bf35,0x3ec4bf6d,0x80003f80,0xbec43f6d,0x8000bf80,0x3ec4bf6d,
0xbf353f35,0xbf6d3ec4,0x3f35bf35,0x3f6dbec4,0xbf800000,0xbf6dbec4,0x3f800000,0x3f6d3ec4,0xbf35bf35,0xbec4bf6d,0x3f353f35,0x3ec43f6d,
0x3f800000,0x3f6d3ec4,0xbf800000,0xbf6dbec4,0x3f353f35,0x3ec43f6d,0xbf35bf35,0xbec4bf6d,0x3f80,0xbec43f6d,0xbf80,0x3ec4bf6d,
0xbf353f35,0xbf6d3ec4,0x3f35bf35,0x3f6dbec4,
};
constexpr int TB_F = 0, TB_E = 512, TB_P2 = 1024;

enum { C_EP = 0, C_Z1 = 32, C_Z2 = 96, C_H3 = 128, C_U = 160, C_X = 288, C_TOTAL = 512 };
struct Scratch {
  unsigned cnt[C_TOTAL];
  uint32_t moda[8 * 2 * D_];
  uint32_t mod[4 * D_ + 256];
  uint32_t z1[120 * 5120];
  uint32_t z2[128 * 4800];
  uint8_t h3[32 * 18 * 4096];
  uint8_t u[72 * D_ * 128];
};
__device__ __align__(1024) Scratch g_s;

#define HOLDA 5
#define GOAT 0
#define H3W 0
#define X1K 10
#ifndef NV1
#define NV1 12
#endif
#ifndef NV2
#define NV2 20
#endif
#define GDEP 3
#define TRK0 50
#define W0N 3
#define TRKC 350
#define HD1 150
#define STRESS 0
#define EH 7
#define KNOB0 0

#define FAILCNT(k) do {} while (0)
#define CK(k) do {} while (0)
#define CKX(k) do {} while (0)
#define TS(k) do {} while (0)
#define TSC(k) do {} while (0)
struct Maps { CUtensorMap z1, z2[2], w1a, w1b, h3, w2, wf[4], wm; };
struct Params {
  const __nv_bfloat16 *x, *c, *wmod;
  Scratch* s;
  const uint4* tab;
  const __nv_bfloat16 *wr, *wi, *w1, *w2, *b1, *b2;
  uint32_t* out;
};

__device__ __forceinline__ uint32_t smem_u32(const void* p) { return (uint32_t)__cvta_generic_to_shared(p); }
__device__ __forceinline__ void mbar_init(uint32_t b, int c) { asm volatile("mbarrier.init.shared::cta.b64 [%0], %1;" ::"r"(b), "r"(c)); }
__device__ __forceinline__ void mbar_expect(uint32_t b, int bytes) { asm volatile("mbarrier.arrive.expect_tx.shared::cta.b64 _, [%0], %1;" ::"r"(b), "r"(bytes) : "memory"); }
__device__ __forceinline__ void mbar_arrive(uint32_t b) { asm volatile("mbarrier.arrive.shared::cta.b64 _, [%0];" ::"r"(b) : "memory"); }
#define MBAR_WAIT(SEM)                                                                                                         \
  asm volatile("{\n.reg .pred p;\n.reg .u32 it;\nmov.u32 it, 0;\nW:\nmbarrier.try_wait.parity" SEM ".shared::cta.b64 p, [%0], %1;\n" \
               "@p bra.uni D;\nadd.u32 it, it, 1;\nsetp.lt.u32 p, it, 0x400000;\n@p bra.uni W;\ntrap;\nD:\n}" ::"r"(b), "r"(ph) : "memory")
__device__ __forceinline__ void mbar_wait(uint32_t b, int ph) { MBAR_WAIT(""); }
__device__ __forceinline__ uint32_t mbar_test(uint32_t b, int ph) {
  uint32_t ok;
  asm volatile("{\n.reg .pred p;\nmbarrier.test_wait.parity.shared::cta.b64 p, [%1], %2;\nselp.u32 %0, 1, 0, p;\n}\n" : "=r"(ok) : "r"(b), "r"(ph) : "memory");
  return ok;
}
__device__ __forceinline__ void tma2d(uint32_t dst, const CUtensorMap* m, int c0, int c1, uint32_t bar) {
  asm volatile("cp.async.bulk.tensor.2d.shared::cluster.global.mbarrier::complete_tx::bytes [%0], [%1, {%3, %4}], [%2];" ::"r"(dst), "l"(m), "r"(bar), "r"(c0), "r"(c1) : "memory");
}
__device__ __forceinline__ uint64_t pol_ef() { uint64_t p; asm("createpolicy.fractional.L2::evict_first.b64 %0, 1.0;" : "=l"(p)); return p; }
__device__ __forceinline__ void tma3d_ef(uint32_t dst, const CUtensorMap* m, int c1, int c2, uint32_t bar) {
  asm volatile("cp.async.bulk.tensor.3d.shared::cluster.global.mbarrier::complete_tx::bytes.L2::cache_hint [%0], [%1, {%3, %4, %5}], [%2], %6;" ::"r"(dst), "l"(m), "r"(bar), "r"(0), "r"(c1), "r"(c2), "l"(pol_ef()) : "memory");
}
__device__ __forceinline__ void tma4d_ef(uint32_t dst, const CUtensorMap* m, int c1, int c2, int c3, uint32_t bar) {
  asm volatile("cp.async.bulk.tensor.4d.shared::cluster.global.mbarrier::complete_tx::bytes.L2::cache_hint [%0], [%1, {%3, %7, %4, %5}], [%2], %6;" ::"r"(dst), "l"(m), "r"(bar), "r"(0), "r"(c2), "r"(c3), "l"(pol_ef()), "r"(c1) : "memory");
}
__device__ __forceinline__ void bulk_ld(uint32_t dst, const void* src, int bytes, uint32_t bar) {
  asm volatile("cp.async.bulk.shared::cluster.global.mbarrier::complete_tx::bytes [%0], [%1], %2, [%3];" ::"r"(dst), "l"(src), "r"(bytes), "r"(bar) : "memory");
}
__device__ __forceinline__ void bulk_st(void* dst, uint32_t src, int bytes) {
  asm volatile("cp.async.bulk.global.shared::cta.bulk_group [%0], [%1], %2;" ::"l"(dst), "r"(src), "r"(bytes) : "memory");
}
__device__ __forceinline__ void tma_st2d(const CUtensorMap* m, uint32_t src, int c0, int c1) {
  asm volatile("cp.async.bulk.tensor.2d.global.shared::cta.bulk_group [%0, {%2, %3}], [%1];" ::"l"(m), "r"(src), "r"(c0), "r"(c1) : "memory");
}
__device__ __forceinline__ void tma_st3d(const CUtensorMap* m, uint32_t src, int c0, int c1, int c2) {
  asm volatile("cp.async.bulk.tensor.3d.global.shared::cta.bulk_group [%0, {%2, %3, %4}], [%1];" ::"l"(m), "r"(src), "r"(c0), "r"(c1), "r"(c2) : "memory");
}
__device__ __forceinline__ void bulk_commit_wait_read() {
  asm volatile("cp.async.bulk.commit_group;" ::: "memory");
  asm volatile("cp.async.bulk.wait_group.read 0;" ::: "memory");
}
__device__ __forceinline__ void bulk_commit_wait() {
  asm volatile("cp.async.bulk.commit_group;" ::: "memory");
  asm volatile("cp.async.bulk.wait_group 0;" ::: "memory");
}
__device__ __forceinline__ void prefetch_l2(const void* p, int bytes) {
  asm volatile("cp.async.bulk.prefetch.L2.global [%0], %1;" ::"l"(p), "r"(bytes) : "memory");
}
__device__ __forceinline__ void wg_fence() { asm volatile("wgmma.fence.sync.aligned;" ::: "memory"); }
__device__ __forceinline__ void wg_commit() { asm volatile("wgmma.commit_group.sync.aligned;" ::: "memory"); }
template <int N> __device__ __forceinline__ void wg_wait() { asm volatile("wgmma.wait_group.sync.aligned %0;" ::"n"(N) : "memory"); }
template <int N> __device__ __forceinline__ void reg_fence(float (&d)[N]) {
#pragma unroll
  for (int i = 0; i < N; i++) asm volatile("" : "+f"(d[i])::"memory");
}
__device__ __forceinline__ void fence_async_smem() { asm volatile("fence.proxy.async.shared::cta;" ::: "memory"); }
__device__ __forceinline__ void fence_async_glb() { asm volatile("fence.proxy.async.global;" ::: "memory"); }
__device__ __forceinline__ uint32_t ld_rlx(const void* p) { uint32_t v; asm volatile("ld.relaxed.gpu.global.b32 %0, [%1];" : "=r"(v) : "l"(p) : "memory"); return v; }
__device__ __forceinline__ uint2 ld_rlx2(const void* p) { uint2 v; asm volatile("ld.relaxed.gpu.global.v2.b32 {%0,%1}, [%2];" : "=r"(v.x), "=r"(v.y) : "l"(p) : "memory"); return v; }
__device__ __forceinline__ uint4 ld_rlx4(const void* p) { uint4 v; asm volatile("ld.relaxed.gpu.global.v4.b32 {%0,%1,%2,%3}, [%4];" : "=r"(v.x), "=r"(v.y), "=r"(v.z), "=r"(v.w) : "l"(p) : "memory"); return v; }
__device__ __forceinline__ uint32_t ld_nc(const void* p) { uint32_t v; asm volatile("ld.global.nc.L1::no_allocate.b32 %0, [%1];" : "=r"(v) : "l"(p) : "memory"); return v; }
__device__ __forceinline__ uint4 ld_nc4(const void* p) { uint4 v; asm volatile("ld.global.nc.v4.b32 {%0,%1,%2,%3}, [%4];" : "=r"(v.x), "=r"(v.y), "=r"(v.z), "=r"(v.w) : "l"(p) : "memory"); return v; }
__device__ __forceinline__ uint32_t lds(uint32_t a) { uint32_t v; asm volatile("ld.shared.b32 %0, [%1];" : "=r"(v) : "r"(a) : "memory"); return v; }
__device__ __forceinline__ uint2 lds2(uint32_t a) { uint2 v; asm volatile("ld.shared.v2.b32 {%0,%1}, [%2];" : "=r"(v.x), "=r"(v.y) : "r"(a) : "memory"); return v; }
__device__ __forceinline__ void lds2_if(int on, uint2& v, uint32_t a) { asm volatile("{\n.reg .pred p;\nsetp.ne.u32 p, %3, 0;\n@p ld.shared.v2.b32 {%0,%1}, [%2];\n}" : "+r"(v.x), "+r"(v.y) : "r"(a), "r"(on) : "memory"); }
__device__ __forceinline__ uint4 lds4(uint32_t a) { uint4 v; asm volatile("ld.shared.v4.b32 {%0,%1,%2,%3}, [%4];" : "=r"(v.x), "=r"(v.y), "=r"(v.z), "=r"(v.w) : "r"(a) : "memory"); return v; }
__device__ __forceinline__ float lds_bf(uint32_t a) { uint32_t v; asm volatile("ld.shared.u16 %0, [%1];" : "=r"(v) : "r"(a) : "memory"); return __uint_as_float(v << 16); }
__device__ __forceinline__ void sts(uint32_t a, uint32_t v) { asm volatile("st.shared.b32 [%0], %1;" ::"r"(a), "r"(v) : "memory"); }
__device__ __forceinline__ void sts2(uint32_t a, uint32_t v0, uint32_t v1) { asm volatile("st.shared.v2.b32 [%0], {%1,%2};" ::"r"(a), "r"(v0), "r"(v1) : "memory"); }
__device__ __forceinline__ void sts4(uint32_t a, uint32_t v0, uint32_t v1, uint32_t v2, uint32_t v3) { asm volatile("st.shared.v4.b32 [%0], {%1,%2,%3,%4};" ::"r"(a), "r"(v0), "r"(v1), "r"(v2), "r"(v3) : "memory"); }
__device__ __forceinline__ void bar_sync(int id, int n) { asm volatile("bar.sync %0, %1;" ::"r"(id), "r"(n) : "memory"); }
__device__ __forceinline__ void bar_arrive(int id, int n) { asm volatile("bar.arrive %0, %1;" ::"r"(id), "r"(n) : "memory"); }
__device__ __forceinline__ void red_add(unsigned* p, unsigned v) { asm volatile("red.relaxed.gpu.global.add.u32 [%0], %1;" ::"l"(p), "r"(v) : "memory"); }
__device__ __forceinline__ bool any(bool p) { return __any_sync(0xffffffffu, p); }
__device__ __forceinline__ void pause(unsigned clks) {
  asm volatile("{\n.reg .pred p;\n.reg .u32 a, b;\nmov.u32 a, %%clock;\nW:\nmov.u32 b, %%clock;\nsub.u32 b, b, a;\nsetp.lt.s32 p, b, %0;\n@p bra.uni W;\n}" ::"r"(clks) : "memory");
}
__device__ __forceinline__ void red_bf16x8(uint32_t* p, uint32_t a, uint32_t b, uint32_t c, uint32_t d) {
  asm volatile("red.relaxed.gpu.global.add.noftz.v4.bf16x2 [%0], {%1,%2,%3,%4};" ::"l"(p), "r"(a), "r"(b), "r"(c), "r"(d) : "memory");
}
__device__ __forceinline__ void red_bf16x4(uint32_t* p, uint32_t a, uint32_t b) {
  asm volatile("red.relaxed.gpu.global.add.noftz.v2.bf16x2 [%0], {%1,%2};" ::"l"(p), "r"(a), "r"(b) : "memory");
}
constexpr int SPIN_MAX = 1 << 20;
__device__ __forceinline__ uint32_t ld_acq(const void* p) { uint32_t v; asm volatile("ld.acquire.gpu.global.b32 %0, [%1];" : "=r"(v) : "l"(p) : "memory"); return v; }
template <bool ACQ = false> __device__ __forceinline__ void wait_cnt(const unsigned* p, unsigned target) {
  int it = 0;
  while (any((int)((ACQ ? ld_acq(p) : ld_rlx(p)) - target) < 0) && ++it < SPIN_MAX) {}
}
__device__ __forceinline__ uint32_t pack_bf16(float lo, float hi) { uint32_t r; asm("cvt.rn.bf16x2.f32 %0, %1, %2;" : "=r"(r) : "f"(hi), "f"(lo)); return r; }
__device__ __forceinline__ float bf_lo(uint32_t v) { return __uint_as_float(v << 16); }
__device__ __forceinline__ float bf_hi(uint32_t v) { return __uint_as_float(v & 0xffff0000u); }
__device__ __forceinline__ uint32_t hadd2(uint32_t a, uint32_t b) { uint32_t r; asm("add.rn.bf16x2 %0, %1, %2;" : "=r"(r) : "r"(a), "r"(b)); return r; }
__device__ __forceinline__ uint32_t hmul2(uint32_t a, uint32_t b) { uint32_t r; asm("mul.rn.bf16x2 %0, %1, %2;" : "=r"(r) : "r"(a), "r"(b)); return r; }
__device__ __forceinline__ uint32_t hfma2(uint32_t a, uint32_t b, uint32_t c) { uint32_t r; asm("fma.rn.bf16x2 %0, %1, %2, %3;" : "=r"(r) : "r"(a), "r"(b), "r"(c)); return r; }
__device__ __forceinline__ float rbf(float x) { uint32_t r; asm("cvt.rn.bf16x2.f32 %0, %1, %2;" : "=r"(r) : "f"(x), "f"(0.0f)); return __uint_as_float(r); }
__device__ __forceinline__ void stmatrix4(uint32_t a, uint32_t r0, uint32_t r1, uint32_t r2, uint32_t r3) {
  asm volatile("stmatrix.sync.aligned.m8n8.x4.shared.b16 [%0], {%1,%2,%3,%4};" ::"r"(a), "r"(r0), "r"(r1), "r"(r2), "r"(r3) : "memory");
}
__device__ __forceinline__ void stmatrix2(uint32_t a, uint32_t r0, uint32_t r1) {
  asm volatile("stmatrix.sync.aligned.m8n8.x2.shared.b16 [%0], {%1,%2};" ::"r"(a), "r"(r0), "r"(r1) : "memory");
}
__device__ __forceinline__ uint32_t movm(uint32_t a) { uint32_t r; asm("movmatrix.sync.aligned.m8n8.trans.b16 %0, %1;" : "=r"(r) : "r"(a)); return r; }
template <bool ACC> __device__ __forceinline__ void mma16(float* d, uint32_t a0, uint32_t a1, uint32_t a2, uint32_t a3, uint32_t b0, uint32_t b1) {
  if (ACC) asm("mma.sync.aligned.m16n8k16.row.col.f32.bf16.bf16.f32 {%0,%1,%2,%3}, {%4,%5,%6,%7}, {%8,%9}, {%0,%1,%2,%3};"
               : "+f"(d[0]), "+f"(d[1]), "+f"(d[2]), "+f"(d[3]) : "r"(a0), "r"(a1), "r"(a2), "r"(a3), "r"(b0), "r"(b1));
  else asm("mma.sync.aligned.m16n8k16.row.col.f32.bf16.bf16.f32 {%0,%1,%2,%3}, {%4,%5,%6,%7}, {%8,%9}, {%10,%10,%10,%10};"
           : "=f"(d[0]), "=f"(d[1]), "=f"(d[2]), "=f"(d[3]) : "r"(a0), "r"(a1), "r"(a2), "r"(a3), "r"(b0), "r"(b1), "f"(0.f));
}
__device__ __forceinline__ uint32_t pin(uint32_t v) { uint32_t r; asm volatile("shfl.sync.bfly.b32 %0, %1, 0, 31, 0xffffffff;" : "=r"(r) : "r"(v)); return r; }
template <class T> __device__ __forceinline__ T* pin(T* p) {
  const uint64_t a = reinterpret_cast<uint64_t>(p);
  return reinterpret_cast<T*>((uint64_t)pin((uint32_t)a) | ((uint64_t)pin((uint32_t)(a >> 32)) << 32));
}
__device__ __forceinline__ uint32_t upin(uint32_t v) { return __shfl_sync(0xffffffffu, v, 0); }
template <class T> __device__ __forceinline__ T* upin(T* p) {
  const uint64_t a = reinterpret_cast<uint64_t>(p);
  return reinterpret_cast<T*>((uint64_t)upin((uint32_t)a) | ((uint64_t)upin((uint32_t)(a >> 32)) << 32));
}
__device__ __forceinline__ int lane_id() { int v; asm volatile("mov.u32 %0, %%laneid;" : "=r"(v)); return v; }
__device__ __forceinline__ bool elect() {
  uint32_t p;
  asm volatile("{\n.reg .pred P;\nelect.sync _|P, 0xffffffff;\nselp.u32 %0, 1, 0, P;\n}" : "=r"(p));
  return p;
}
__device__ __forceinline__ uint32_t set_tag(uint32_t w, uint32_t tag) { uint32_t r; asm("lop3.b32 %0, %1, 0xfffffffe, %2, 0xea;" : "=r"(r) : "r"(w), "r"(tag)); return r; }
__device__ __forceinline__ uint32_t bitsel(uint32_t w, uint32_t m, uint32_t o) { uint32_t r; asm("lop3.b32 %0, %1, %2, %3, 0xe2;" : "=r"(r) : "r"(w), "r"(m), "r"(o)); return r; }
__device__ __forceinline__ uint32_t or3(uint32_t a, uint32_t b, uint32_t c) { uint32_t r; asm("lop3.b32 %0, %1, %2, %3, 0xfe;" : "=r"(r) : "r"(a), "r"(b), "r"(c)); return r; }
__device__ __forceinline__ uint32_t diff2(uint32_t a, uint32_t b, uint32_t tag) { uint32_t r; asm("lop3.b32 %0, %1, %2, %3, 0x7e;" : "=r"(r) : "r"(a), "r"(b), "r"(tag)); return r; }
__device__ __forceinline__ float2 cmul(float2 a, float2 b) { return make_float2(a.x * b.x - a.y * b.y, a.x * b.y + a.y * b.x); }

template<int TB> __device__ __forceinline__ void wgmma_ss_160_0(float (&d)[96], uint32_t al, uint32_t ah, uint32_t bl, uint32_t bh) {
  asm volatile("{\n.reg .b64 da, db;\nmov.b64 da, {%80, %81};\nmov.b64 db, {%82, %83};\n"
    "wgmma.mma_async.sync.aligned.m64n160k16.f32.bf16.bf16 {%0,%1,%2,%3,%4,%5,%6,%7,%8,%9,%10,%11,%12,%13,%14,%15,%16,%17,%18,%19,%20,%21,%22,%23,%24,%25,%26,%27,%28,%29,%30,%31,%32,%33,%34,%35,%36,%37,%38,%39,%40,%41,%42,%43,%44,%45,%46,%47,%48,%49,%50,%51,%52,%53,%54,%55,%56,%57,%58,%59,%60,%61,%62,%63,%64,%65,%66,%67,%68,%69,%70,%71,%72,%73,%74,%75,%76,%77,%78,%79}, da, db, 1, 1, 1, 1, %84;\n}\n"
    : "+f"(d[0]),"+f"(d[1]),"+f"(d[2]),"+f"(d[3]),"+f"(d[4]),"+f"(d[5]),"+f"(d[6]),"+f"(d[7]),"+f"(d[8]),"+f"(d[9]),"+f"(d[10]),"+f"(d[11]),"+f"(d[12]),"+f"(d[13]),"+f"(d[14]),"+f"(d[15]),"+f"(d[16]),"+f"(d[17]),"+f"(d[18]),"+f"(d[19]),"+f"(d[20]),"+f"(d[21]),"+f"(d[22]),"+f"(d[23]),"+f"(d[24]),"+f"(d[25]),"+f"(d[26]),"+f"(d[27]),"+f"(d[28]),"+f"(d[29]),"+f"(d[30]),"+f"(d[31]),"+f"(d[32]),"+f"(d[33]),"+f"(d[34]),"+f"(d[35]),"+f"(d[36]),"+f"(d[37]),"+f"(d[38]),"+f"(d[39]),"+f"(d[40]),"+f"(d[41]),"+f"(d[42]),"+f"(d[43]),"+f"(d[44]),"+f"(d[45]),"+f"(d[46]),"+f"(d[47]),"+f"(d[48]),"+f"(d[49]),"+f"(d[50]),"+f"(d[51]),"+f"(d[52]),"+f"(d[53]),"+f"(d[54]),"+f"(d[55]),"+f"(d[56]),"+f"(d[57]),"+f"(d[58]),"+f"(d[59]),"+f"(d[60]),"+f"(d[61]),"+f"(d[62]),"+f"(d[63]),"+f"(d[64]),"+f"(d[65]),"+f"(d[66]),"+f"(d[67]),"+f"(d[68]),"+f"(d[69]),"+f"(d[70]),"+f"(d[71]),"+f"(d[72]),"+f"(d[73]),"+f"(d[74]),"+f"(d[75]),"+f"(d[76]),"+f"(d[77]),"+f"(d[78]),"+f"(d[79])
    : "r"(al), "r"(ah), "r"(bl), "r"(bh), "n"(TB));
}
template<int TB> __device__ __forceinline__ void wgmma_ss_144_0(float (&d)[96], uint32_t al, uint32_t ah, uint32_t bl, uint32_t bh) {
  asm volatile("{\n.reg .b64 da, db;\nmov.b64 da, {%72, %73};\nmov.b64 db, {%74, %75};\n"
    "wgmma.mma_async.sync.aligned.m64n144k16.f32.bf16.bf16 {%0,%1,%2,%3,%4,%5,%6,%7,%8,%9,%10,%11,%12,%13,%14,%15,%16,%17,%18,%19,%20,%21,%22,%23,%24,%25,%26,%27,%28,%29,%30,%31,%32,%33,%34,%35,%36,%37,%38,%39,%40,%41,%42,%43,%44,%45,%46,%47,%48,%49,%50,%51,%52,%53,%54,%55,%56,%57,%58,%59,%60,%61,%62,%63,%64,%65,%66,%67,%68,%69,%70,%71}, da, db, 1, 1, 1, 1, %76;\n}\n"
    : "+f"(d[0]),"+f"(d[1]),"+f"(d[2]),"+f"(d[3]),"+f"(d[4]),"+f"(d[5]),"+f"(d[6]),"+f"(d[7]),"+f"(d[8]),"+f"(d[9]),"+f"(d[10]),"+f"(d[11]),"+f"(d[12]),"+f"(d[13]),"+f"(d[14]),"+f"(d[15]),"+f"(d[16]),"+f"(d[17]),"+f"(d[18]),"+f"(d[19]),"+f"(d[20]),"+f"(d[21]),"+f"(d[22]),"+f"(d[23]),"+f"(d[24]),"+f"(d[25]),"+f"(d[26]),"+f"(d[27]),"+f"(d[28]),"+f"(d[29]),"+f"(d[30]),"+f"(d[31]),"+f"(d[32]),"+f"(d[33]),"+f"(d[34]),"+f"(d[35]),"+f"(d[36]),"+f"(d[37]),"+f"(d[38]),"+f"(d[39]),"+f"(d[40]),"+f"(d[41]),"+f"(d[42]),"+f"(d[43]),"+f"(d[44]),"+f"(d[45]),"+f"(d[46]),"+f"(d[47]),"+f"(d[48]),"+f"(d[49]),"+f"(d[50]),"+f"(d[51]),"+f"(d[52]),"+f"(d[53]),"+f"(d[54]),"+f"(d[55]),"+f"(d[56]),"+f"(d[57]),"+f"(d[58]),"+f"(d[59]),"+f"(d[60]),"+f"(d[61]),"+f"(d[62]),"+f"(d[63]),"+f"(d[64]),"+f"(d[65]),"+f"(d[66]),"+f"(d[67]),"+f"(d[68]),"+f"(d[69]),"+f"(d[70]),"+f"(d[71])
    : "r"(al), "r"(ah), "r"(bl), "r"(bh), "n"(TB));
}
template<int TB> __device__ __forceinline__ void wgmma_ss_96_0(float (&d)[96], uint32_t al, uint32_t ah, uint32_t bl, uint32_t bh) {
  asm volatile("{\n.reg .b64 da, db;\nmov.b64 da, {%48, %49};\nmov.b64 db, {%50, %51};\n"
    "wgmma.mma_async.sync.aligned.m64n96k16.f32.bf16.bf16 {%0,%1,%2,%3,%4,%5,%6,%7,%8,%9,%10,%11,%12,%13,%14,%15,%16,%17,%18,%19,%20,%21,%22,%23,%24,%25,%26,%27,%28,%29,%30,%31,%32,%33,%34,%35,%36,%37,%38,%39,%40,%41,%42,%43,%44,%45,%46,%47}, da, db, 1, 1, 1, 1, %52;\n}\n"
    : "+f"(d[0]),"+f"(d[1]),"+f"(d[2]),"+f"(d[3]),"+f"(d[4]),"+f"(d[5]),"+f"(d[6]),"+f"(d[7]),"+f"(d[8]),"+f"(d[9]),"+f"(d[10]),"+f"(d[11]),"+f"(d[12]),"+f"(d[13]),"+f"(d[14]),"+f"(d[15]),"+f"(d[16]),"+f"(d[17]),"+f"(d[18]),"+f"(d[19]),"+f"(d[20]),"+f"(d[21]),"+f"(d[22]),"+f"(d[23]),"+f"(d[24]),"+f"(d[25]),"+f"(d[26]),"+f"(d[27]),"+f"(d[28]),"+f"(d[29]),"+f"(d[30]),"+f"(d[31]),"+f"(d[32]),"+f"(d[33]),"+f"(d[34]),"+f"(d[35]),"+f"(d[36]),"+f"(d[37]),"+f"(d[38]),"+f"(d[39]),"+f"(d[40]),"+f"(d[41]),"+f"(d[42]),"+f"(d[43]),"+f"(d[44]),"+f"(d[45]),"+f"(d[46]),"+f"(d[47])
    : "r"(al), "r"(ah), "r"(bl), "r"(bh), "n"(TB));
}
template<int TB> __device__ __forceinline__ void wgmma_ss_96_48(float (&d)[96], uint32_t al, uint32_t ah, uint32_t bl, uint32_t bh) {
  asm volatile("{\n.reg .b64 da, db;\nmov.b64 da, {%48, %49};\nmov.b64 db, {%50, %51};\n"
    "wgmma.mma_async.sync.aligned.m64n96k16.f32.bf16.bf16 {%0,%1,%2,%3,%4,%5,%6,%7,%8,%9,%10,%11,%12,%13,%14,%15,%16,%17,%18,%19,%20,%21,%22,%23,%24,%25,%26,%27,%28,%29,%30,%31,%32,%33,%34,%35,%36,%37,%38,%39,%40,%41,%42,%43,%44,%45,%46,%47}, da, db, 1, 1, 1, 1, %52;\n}\n"
    : "+f"(d[48]),"+f"(d[49]),"+f"(d[50]),"+f"(d[51]),"+f"(d[52]),"+f"(d[53]),"+f"(d[54]),"+f"(d[55]),"+f"(d[56]),"+f"(d[57]),"+f"(d[58]),"+f"(d[59]),"+f"(d[60]),"+f"(d[61]),"+f"(d[62]),"+f"(d[63]),"+f"(d[64]),"+f"(d[65]),"+f"(d[66]),"+f"(d[67]),"+f"(d[68]),"+f"(d[69]),"+f"(d[70]),"+f"(d[71]),"+f"(d[72]),"+f"(d[73]),"+f"(d[74]),"+f"(d[75]),"+f"(d[76]),"+f"(d[77]),"+f"(d[78]),"+f"(d[79]),"+f"(d[80]),"+f"(d[81]),"+f"(d[82]),"+f"(d[83]),"+f"(d[84]),"+f"(d[85]),"+f"(d[86]),"+f"(d[87]),"+f"(d[88]),"+f"(d[89]),"+f"(d[90]),"+f"(d[91]),"+f"(d[92]),"+f"(d[93]),"+f"(d[94]),"+f"(d[95])
    : "r"(al), "r"(ah), "r"(bl), "r"(bh), "n"(TB));
}
__device__ __forceinline__ void wgmma_rs_72(float (&d)[36], uint32_t a0, uint32_t a1, uint32_t a2, uint32_t a3, uint32_t bl, uint32_t bh, int sd) {
  asm volatile("{\n.reg .pred p;\n.reg .b64 db;\nsetp.ne.b32 p, %42, 0;\nmov.b64 db, {%40, %41};\n"
    "wgmma.mma_async.sync.aligned.m64n72k16.f32.bf16.bf16 {%0,%1,%2,%3,%4,%5,%6,%7,%8,%9,%10,%11,%12,%13,%14,%15,%16,%17,%18,%19,%20,%21,%22,%23,%24,%25,%26,%27,%28,%29,%30,%31,%32,%33,%34,%35}, {%36,%37,%38,%39}, db, p, 1, 1, 1;\n}\n"
    : "+f"(d[0]),"+f"(d[1]),"+f"(d[2]),"+f"(d[3]),"+f"(d[4]),"+f"(d[5]),"+f"(d[6]),"+f"(d[7]),"+f"(d[8]),"+f"(d[9]),"+f"(d[10]),"+f"(d[11]),"+f"(d[12]),"+f"(d[13]),"+f"(d[14]),"+f"(d[15]),"+f"(d[16]),"+f"(d[17]),"+f"(d[18]),"+f"(d[19]),"+f"(d[20]),"+f"(d[21]),"+f"(d[22]),"+f"(d[23]),"+f"(d[24]),"+f"(d[25]),"+f"(d[26]),"+f"(d[27]),"+f"(d[28]),"+f"(d[29]),"+f"(d[30]),"+f"(d[31]),"+f"(d[32]),"+f"(d[33]),"+f"(d[34]),"+f"(d[35])
    : "r"(a0), "r"(a1), "r"(a2), "r"(a3), "r"(bl), "r"(bh), "r"(sd));
}
__device__ __forceinline__ void wgmma_rs_48(float (&d)[24], uint32_t a0, uint32_t a1, uint32_t a2, uint32_t a3, uint32_t bl, uint32_t bh, int sd) {
  asm volatile("{\n.reg .pred p;\n.reg .b64 db;\nsetp.ne.b32 p, %30, 0;\nmov.b64 db, {%28, %29};\n"
    "wgmma.mma_async.sync.aligned.m64n48k16.f32.bf16.bf16 {%0,%1,%2,%3,%4,%5,%6,%7,%8,%9,%10,%11,%12,%13,%14,%15,%16,%17,%18,%19,%20,%21,%22,%23}, {%24,%25,%26,%27}, db, p, 1, 1, 1;\n}\n"
    : "+f"(d[0]),"+f"(d[1]),"+f"(d[2]),"+f"(d[3]),"+f"(d[4]),"+f"(d[5]),"+f"(d[6]),"+f"(d[7]),"+f"(d[8]),"+f"(d[9]),"+f"(d[10]),"+f"(d[11]),"+f"(d[12]),"+f"(d[13]),"+f"(d[14]),"+f"(d[15]),"+f"(d[16]),"+f"(d[17]),"+f"(d[18]),"+f"(d[19]),"+f"(d[20]),"+f"(d[21]),"+f"(d[22]),"+f"(d[23])
    : "r"(a0), "r"(a1), "r"(a2), "r"(a3), "r"(bl), "r"(bh), "r"(sd));
}
template<int N,int OFF,int TB> __device__ __forceinline__ void wgmma_ss(float (&d)[96], uint32_t al, uint32_t ah, uint32_t bl, uint32_t bh) {
  if constexpr (N==160 && OFF==0) wgmma_ss_160_0<TB>(d, al, ah, bl, bh);
  else if constexpr (N==144 && OFF==0) wgmma_ss_144_0<TB>(d, al, ah, bl, bh);
  else if constexpr (N==96 && OFF==0) wgmma_ss_96_0<TB>(d, al, ah, bl, bh);
  else if constexpr (N==96 && OFF==48) wgmma_ss_96_48<TB>(d, al, ah, bl, bh);
}

__device__ __forceinline__ void dft3(float2& a, float2& b, float2& c) {
  const float s = 0.86602540378443864676f;
  float2 t = make_float2(b.x + c.x, b.y + c.y), d = make_float2(b.x - c.x, b.y - c.y);
  float2 m = make_float2(fmaf(-0.5f, t.x, a.x), fmaf(-0.5f, t.y, a.y));
  a = make_float2(a.x + t.x, a.y + t.y);
  b = make_float2(fmaf(s, d.y, m.x), fmaf(-s, d.x, m.y));
  c = make_float2(fmaf(-s, d.y, m.x), fmaf(s, d.x, m.y));
}
__device__ __forceinline__ void dft9(float2 (&x)[9]) {
  const float2 w1 = make_float2(0.76604444311897803520f, -0.64278760968653932632f);
  const float2 w2 = make_float2(0.17364817766693034885f, -0.98480775301220805937f);
  const float2 w4 = make_float2(-0.93969262078590838405f, -0.34202014332566873304f);
  dft3(x[0], x[3], x[6]); dft3(x[1], x[4], x[7]); dft3(x[2], x[5], x[8]);
  x[4] = cmul(x[4], w1); x[7] = cmul(x[7], w2); x[5] = cmul(x[5], w2); x[8] = cmul(x[8], w4);
  dft3(x[0], x[1], x[2]); dft3(x[3], x[4], x[5]); dft3(x[6], x[7], x[8]);
  float2 t;
  t = x[1]; x[1] = x[3]; x[3] = t;
  t = x[2]; x[2] = x[6]; x[6] = t;
  t = x[5]; x[5] = x[7]; x[7] = t;
}

__device__ __forceinline__ uint32_t* mod_ptr(Scratch* sc, int u, int t128) {
  const int i = t128 & 15;
  return u < 72 ? sc->moda + (t128 >> 4) * (2 * D_) + 16 * u + 2 * (i & 7) + (i >> 3) : sc->mod + 16 * (u - 72) + i;
}
__device__ __forceinline__ void mod_unit(Scratch* sc, int u, int t128, uint32_t sw_, uint32_t bar, int ph, uint32_t rb, uint32_t tag) {
  const int w = t128 >> 5, l = t128 & 31;
  uint32_t b[18];
#pragma unroll
  for (int i = 0; i < 18; i++) b[i] = lds(red + 512 + (72 * w + 4 * i + (l & 3)) * 4);
  const uint32_t sa = pin(sw_ + (144 * w + (l & 7) + 8 * (l >> 4)) * 32 + (((l >> 3) ^ (l >> 2)) & 1) * 16);
  const uint32_t sr = pin(rb + (l >> 2) * 16 + w * 4);
  uint32_t* const dst = pin(mod_ptr(sc, u, t128));
  const int kind = u / 36;
  const float mul = __uint_as_float(pin(__float_as_uint(kind == 0 ? 16.0f : 1.0f))), add = __uint_as_float(pin(__float_as_uint(kind == 1 || kind == 4 ? 1.0f : 0.0f)));
  mbar_wait(bar, ph);
  if (t128 == 0 && u < 72) TS(10);
  float d[3][4];
#pragma unroll
  for (int i = 0; i < 9; i++) {
    uint32_t a0, a1, a2, a3;
    asm volatile("ldmatrix.sync.aligned.m8n8.x4.trans.shared.b16 {%0,%1,%2,%3}, [%4];" : "=r"(a0), "=r"(a1), "=r"(a2), "=r"(a3) : "r"(sa + i * 512) : "memory");
    if (i < 3) mma16<false>(d[i], a0, a1, a2, a3, b[2 * i], b[2 * i + 1]);
    else mma16<true>(d[i % 3], a0, a1, a2, a3, b[2 * i], b[2 * i + 1]);
  }
  if ((l & 3) == 0) { sts(sr, __float_as_uint(d[0][0] + d[1][0] + d[2][0])); sts(sr + 128, __float_as_uint(d[0][2] + d[1][2] + d[2][2])); }
  bar_sync(4, 128);
  const uint4 v = lds4(rb + (l & 15) * 16);
  const float m = rbf(fmaf(rbf((__uint_as_float(v.x) + __uint_as_float(v.y)) + (__uint_as_float(v.z) + __uint_as_float(v.w))), mul, add));
  if (u < 72 || t128 < 16) *dst = __float_as_uint(m) | tag;
}

__device__ __forceinline__ float rsq(float x) { float r; asm("rsqrt.approx.ftz.f32 %0, %1;" : "=f"(r) : "f"(x)); return r; }
__device__ __forceinline__ void ln_stats2(const float (&a)[18], const float (&b)[18], float sc, float& oa, float& ra, float& ob, float& rb) {
  float v[4] = {0.f, 0.f, 0.f, 0.f}, w[4] = {0.f, 0.f, 0.f, 0.f};
#pragma unroll
  for (int i = 0; i < 18; i += 2) {
    v[0] += a[i]; v[1] = fmaf(a[i], a[i], v[1]); v[2] += b[i]; v[3] = fmaf(b[i], b[i], v[3]);
    w[0] += a[i + 1]; w[1] = fmaf(a[i + 1], a[i + 1], w[1]); w[2] += b[i + 1]; w[3] = fmaf(b[i + 1], b[i + 1], w[3]);
  }
#pragma unroll
  for (int e = 0; e < 4; e++) v[e] += w[e];
#pragma unroll
  for (int o = 16; o; o >>= 1) {
#pragma unroll
    for (int e = 0; e < 4; e++) v[e] += __shfl_xor_sync(0xffffffffu, v[e], o);
  }
  const float ma = v[0] * (1.0f / D_), mb = v[2] * (1.0f / D_);
  ra = sc * rsq(fmaxf(fmaf(-ma, ma, v[1] * (1.0f / D_)), 0.f) + 1e-5f);
  rb = sc * rsq(fmaxf(fmaf(-mb, mb, v[3] * (1.0f / D_)), 0.f) + 1e-5f);
  oa = -ma * ra; ob = -mb * rb;
}

__device__ __forceinline__ void ln_stats1(const float (&a)[18], float sc, float& oa, float& ra) {
  float v[3] = {a[0], a[1], a[2]}, w[3] = {a[0] * a[0], a[1] * a[1], a[2] * a[2]};
#pragma unroll
  for (int i = 3; i < 18; i++) { v[i % 3] += a[i]; w[i % 3] = fmaf(a[i], a[i], w[i % 3]); }
  float s = v[0] + v[1] + v[2], q = w[0] + w[1] + w[2];
#pragma unroll
  for (int o = 16; o; o >>= 1) { s += __shfl_xor_sync(0xffffffffu, s, o); q += __shfl_xor_sync(0xffffffffu, q, o); }
  const float m = s * (1.0f / D_);
  ra = sc * rsq(fmaxf(fmaf(-m, m, q * (1.0f / D_)), 0.f) + 1e-5f);
  oa = -m * ra;
}

__device__ __forceinline__ float tmat(int c, int q, int j) {
  const int ph = q == 1 ? 1024 * j : (q >> 1) * (c + 128 * j) + 512 * (q & 1);
  return __cosf((float)(((ph + 1024) & 2047) - 1024) * (6.283185307179586f / 2048.0f));
}
__device__ __forceinline__ uint32_t line_off(int k1, int kap, int pi, int f) {
  int kd = 64 * k1 + 9 * kap;
  if (kap == 0 && k1 > 4) kd -= 288;
  if (kd >= D_) kd -= D_;
  return pi * 2400 + ((min(kd, D_ - kd) ^ f) << 3);
}

struct Ring { uint32_t st, ph; };
template <bool G2, class T> __device__ __forceinline__ void ring_next(T& st, T& ph) {
  if (++st == NST) st = 0;
  ph ^= ((G2 ? 0xDu : 0x1u) >> st) & 1;
}
__device__ __forceinline__ void arrive_if(uint32_t a, uint32_t p) {
  asm volatile("{\n.reg .pred p;\nsetp.ne.u32 p, %1, 0;\n@p mbarrier.arrive.shared::cta.b64 _, [%0];\n}" ::"r"(a), "r"(p) : "memory");
}
template <int NA> __device__ __forceinline__ void reg_fence_n(float (&d)[96]) {
#pragma unroll
  for (int i = 0; i < NA; i++) asm volatile("" : "+f"(d[i])::"memory");
}
template <int MODE>
__device__ __forceinline__ void gemm_main(float (&acc)[96], uint32_t da0, uint32_t da1, uint32_t db0, int wg, Ring& rg,
                                          bool rows, int J, uint32_t* x1p, const uint32_t (&xr)[18]) {
  constexpr int NKB = MODE == 3 ? 36 : 32;
  constexpr uint32_t HA = 0x40000040u, HB = MODE == 3 ? 0xC0000010u : 0x80000020u;
  constexpr uint32_t KA = 2048 >> 4, KB = (MODE == 3 ? 512 : 1024) >> 4;
  constexpr int NA = MODE == 3 ? 72 : MODE == 1 ? 96 : 80;
  const uint32_t t = threadIdx.x & 127;
  const uint32_t eb = full0 + 8 * NST;
  constexpr uint32_t SP = (MODE == 3 ? STAGE2 : STAGE) >> 4;
  uint32_t pb = 0, prel = 0, ok = 0, sn = rg.st * SP;
  int n = MODE != 3 ? X1K + 2 * wg : wg ? NKB - J : NKB, nh = 0, ng = MODE == 3 && !wg;
#pragma unroll 1
  for (int pass = MODE == 3 ? 0 : -1;; pass++) {
#pragma unroll 1
    do {
      mbar_wait(full0 + 8 * rg.st, rg.ph);
#pragma unroll 1
      do {
      const uint32_t so = sn, cb = eb + 8 * rg.st;
      reg_fence_n<NA>(acc);
      if (MODE == 1 && wg) {
        wg_fence();
#pragma unroll
        for (int k = 0; k < 4; k++) wgmma_ss<96, 48, 1>(acc, da1 + so + k * KA, HA, db0 + so + k * KB, HB);
        wg_commit();
      }
      wg_fence();
#pragma unroll
      for (int k = 0; k < 4; k++) {
        if (k == 2) asm volatile("{\n.reg .pred p;\nsetp.eq.s32 p, %0, %1;\n@p bar.arrive 1, 256;\n}" ::"r"(n), "r"(ng) : "memory");
        if (k == 1 && MODE != 1) { wg_commit(); wg_wait<1>(); arrive_if(pb, prel); }
        if (k == 2) { ring_next<MODE == 3>(rg.st, rg.ph); sn = rg.st * SP; ok = mbar_test(full0 + 8 * rg.st, rg.ph); }
        if (MODE == 0) wgmma_ss<160, 0, 1>(acc, da0 + so + k * KA, HA, db0 + so + k * KB, HB);
        else if (MODE == 3) wgmma_ss<144, 0, 1>(acc, da0 + so + k * KA, HA, db0 + so + k * KB, HB);
        else wgmma_ss<96, 0, 1>(acc, da0 + so + k * KA, HA, db0 + so + k * KB, HB);
      }
      wg_commit();
      if (MODE == 1) { wg_wait<1>(); arrive_if(pb, prel); }
      reg_fence_n<NA>(acc);
      pb = cb; prel = t == 0 && (MODE != 0 || n != nh);
      } while (--n && ok);
    } while (n);
    if (pass == wg) break;
    if (MODE != 3 && pass < 0) {
      if (rows) {
#pragma unroll
        for (int i = 0; i < 9; i++) { x1p[32 * i] = xr[i]; x1p[512 * 288 + 32 * i] = xr[9 + i]; }
      }
      n = NKB - X1K - (J + 2) * wg;
      if (!wg) { ng = 1; if (J < NST) nh = NST; }
      continue;
    }
    wg_wait<0>();
    arrive_if(pb, prel);
    prel = 0;
    n = J;
    if (MODE == 0 && J < NST) bar_arrive(11, 256);
    bar_sync(1, 256);
  }
  if (MODE == 0 && J < NST && !wg) bar_sync(11, 256);
  wg_wait<0>();
  reg_fence_n<NA>(acc);
  if (MODE != 3) arrive_if(pb, prel);
}

constexpr float GK1 = 2.0f * 0.7978845608028654f, GK3 = 8.0f * 0.044715f * 0.7978845608028654f;

__device__ __forceinline__ int kb2_order(int i) { const int wv = i / 6; return 6 * (i - 6 * wv) + ((0x431250 >> (4 * wv)) & 7); }

__device__ __forceinline__ int kb2_pos(int kb) { const int hf = kb >= 36, k = kb - 36 * hf, gr = k / 6; return 64 * hf + gr + 6 * ((0x154230 >> (4 * (k - 6 * gr))) & 7); }

__device__ __forceinline__ void wait_flags(const unsigned* p, int idx, unsigned target, uint32_t& ready) {
  int it = 0;
  while (!((ready >> idx) & 1) && it++ < SPIN_MAX) ready = __ballot_sync(0xffffffffu, (int)(ld_rlx(p) - target) >= 0);
}

enum { B_FULL = 0, B_EMPTY = 6, B_S4 = 12, B_S5, B_LAND, B_FLT = B_LAND + 6, B_Z1, B_Z2, B_GO, B_X, B_WM, B_NUM, B_W0 = B_NUM };

__global__ void __launch_bounds__(NTHR, 1)
fused_kernel(const Params p, const __grid_constant__ Maps maps) {
  extern __shared__ __align__(1024) uint8_t smem_raw[];
  const int bx = blockIdx.x, cta = bx < 112 || bx >= 130 ? bx : bx < 114 ? bx + 16 : bx - 2;
  const int tid = threadIdx.x, t128 = tid & 127;
  const int wp = __shfl_sync(0xffffffffu, tid >> 5, 0), wg = wp >> 2;
  const int l = tid & 31, g = l >> 2, t = l & 3;
  Scratch* const sc = p.s;
  const bool rows = cta < 128;
  const int mu = rows ? cta + 4 : cta - 128;
  const int R = mu - 12;

  uint32_t xr[18];
  uint32_t cv[3];
  const unsigned ep0 = ld_rlx(&sc->cnt[C_EP + l]);
  if (tid == 0) TS(0);
  if (wg == 2) {
#pragma unroll
    for (int i = 0; i < 3; i++) cv[i] = ld_nc(reinterpret_cast<const uint32_t*>(p.c) + min(t128 + 128 * i, 287));
    if (wp == 9 && l < 9 && rows) {
      const int h = 9 * cta + l;
      prefetch_l2(reinterpret_cast<const uint8_t*>(p.wmod) + (size_t)(h >> 1) * (12 * D_) + (h & 1) * (2 * D_), 2 * D_);
    }
    if (tid == 256 && mu < 72) {
      mbar_init(full0 + 8 * B_W0, 1);
      fence_async_smem();
      mbar_expect(full0 + 8 * B_W0, 18432);
#pragma unroll 1
      for (int i = 0; i < 3; i++) tma2d(sbase + O_P2 + i * 6144, &maps.wm, 16 * mu, 192 * i, full0 + 8 * B_W0);
    }
    __syncwarp();
#pragma unroll 1
    for (int u = mu < 72 ? mu : 72 + mu; u < 216; u += u < 72 ? 72 : NCTA) if (u < 72 || t128 < 16) *mod_ptr(sc, u, t128) = 0;
    if (wp == 11 && smem_u32(smem_raw) != sbase) __trap();
    if (wp >= 10 && elect()) {
#pragma unroll 1
      for (int i = wp - 10; i < B_NUM; i += 2) mbar_init(full0 + 8 * i, i == B_FLT ? 4 : i == B_WM ? 3 : i < B_S4 ? 2 : 1);
      fence_async_smem();
    }
    __syncwarp();
  } else if (rows) {
    const uint32_t* xs = reinterpret_cast<const uint32_t*>(p.x) + (size_t)(cta + 128 * ((wp & 3) + 8 * wg)) * 288 + l;
#pragma unroll
    for (int i = 0; i < 9; i++) { xr[i] = ld_nc(xs + 32 * i); xr[9 + i] = ld_nc(xs + 512 * 288 + 32 * i); }
  }
  CK(0);
  if (tid == 64 && cta == NCTA - 1) prefetch_l2(p.tab, sizeof(T_TAB));
  __syncwarp();
  auto tag_of = [](unsigned e) { return (e & 0x7fffu) | 0x8000u; };
  const int kap = 8 * ((wp & 3) ^ (wg & 1)) + g;
  uint32_t tb[4], sb1[3], lo[9];
#pragma unroll
  for (int i = 0; i < 4; i++) tb[i] = pin(pack_bf16(tmat(cta, 8 * (i >> 1) + g, t + 8 * (i & 1)), tmat(cta, 8 * (i >> 1) + g, t + 8 * (i & 1) + 4)));
#pragma unroll
  for (int i = 0; i < 3; i++) {
    const int d = 48 * wp + 16 * i + (l & 15);
    sb1[i] = pin(sbase + O_B1 + (l >> 4) * 9216 + (d % 9) * 1024 + (d & 63) * 16);
  }
#pragma unroll
  for (int k1 = 0; k1 < 9; k1++) lo[k1] = pin(sbase + O_Z1 + line_off(k1, kap, 4 * wg + t, cta & 3));
  const uint32_t snt = pin(sbase + O_NRM + ((l & 7) + 8 * (l >> 4)) * 1168 + (48 * wp + (l & 8)) * 2), sn = pin(sbase + O_NRM + wp * 2336 + l * 4);
  const uint32_t smask = pin(t ? 0u : 0xffff0000u);
  const uint32_t* const mp = pin(sc->moda + (cta >> 4) * (2 * D_) + 48 * wp + 2 * g);
  const uint4* const ftab = pin(p.tab + TB_F + (t128 ^ (wg << 5)));

  if (wg == 2) {
#pragma unroll
    for (int i = 0; i < 3; i++) {
      const float c0 = bf_lo(cv[i]), c1 = bf_hi(cv[i]);
      sts(red + 512 + min(t128 + 128 * i, 287) * 4, pack_bf16(__fdividef(c0, 1.0f + __expf(-c0)), __fdividef(c1, 1.0f + __expf(-c1))));
    }
    if (t128 == 0) sts(full0 + 248, ep0 + 1);
    if (wp == 9 && l < 11) asm volatile("prefetch.tensormap [%0];" ::"l"(&maps.z1 + l) : "memory");
    bar_sync(4, 128);
    if (mu < 72) {
      mod_unit(sc, mu, t128, sbase + O_P2, full0 + 8 * B_W0, 0, red, tag_of(upin(ep0) + 1));
      if (t128 == 0) TS(25);
    }
    CK(1);
  }
  const int pi = R / 15, col0 = 20 * (R - 15 * pi);
  const int xu = DF_ * pi + col0, xv = DF_ * (pi ? 16 - pi : 8) + col0;
  auto load_filter = [&](int a) {
    const int x = (a & 1) ? xv : xu;
    const bool wide = (x & 15) > 12;
    mbar_expect(full0 + 8 * B_FLT, wide ? 12288 : 8192);
    tma2d(sbase + O_RAW + a * 12288, &maps.wf[a & 2], x & ~15, 0, full0 + 8 * B_FLT);
    if (wide) tma2d(sbase + O_RAW + a * 12288 + 8192, &maps.wf[(a & 2) + 1], (x & ~15) + 32, 0, full0 + 8 * B_FLT);
  };
  uint4 af[4];
  if (rows) {
    uint2 ms[3], mc[3];
    auto load_mod = [&](uint32_t o = 0) {
#pragma unroll
      for (int i = 0; i < 3; i++) { ms[i] = ld_rlx2(mp + 2 * o + 16 * i); mc[i] = ld_rlx2(mp + 2 * o + D_ + 16 * i); }
    };
    if (wg < 2) {
      float a[18], b[18];
#pragma unroll
      for (int i = 0; i < 9; i++) { a[2 * i] = bf_lo(xr[i]); a[2 * i + 1] = bf_hi(xr[i]); b[2 * i] = bf_lo(xr[9 + i]); b[2 * i + 1] = bf_hi(xr[9 + i]); }
      float oa, ra, ob, rb;
      ln_stats2(a, b, 1.0f, oa, ra, ob, rb);
      CK(1);
      load_mod((__float_as_uint(ra) | __float_as_uint(rb)) >> 31);
#pragma unroll
      for (int i = 0; i < 9; i++) {
        sts(sn + i * 128, pack_bf16(fmaf(a[2 * i], ra, oa), fmaf(a[2 * i + 1], ra, oa)));
        sts(sn + 1168 + i * 128, pack_bf16(fmaf(b[2 * i], rb, ob), fmaf(b[2 * i + 1], rb, ob)));
      }
      CK(2);
      bar_arrive(10, NTHR);
#pragma unroll
      for (int kk = 0; kk < 4; kk++) af[kk] = ld_nc4(ftab + kk * 128);
      bar_sync(1, 256);
      if (tid == 0) TS(2);
    } else {
      bar_sync(10, NTHR);
      load_mod();
      CK(2);
      if (wp >= 10 && elect()) prefetch_l2(reinterpret_cast<const uint8_t*>(wp == 10 ? p.wr : p.wi) + cta * 9248, 9248);
      __syncwarp();
    }
    float rs[3][8];
#pragma unroll
    for (int i = 0; i < 3; i++) {
      uint32_t a0, a1, a2, a3;
      asm volatile("ldmatrix.sync.aligned.m8n8.x4.trans.shared.b16 {%0,%1,%2,%3}, [%4];" : "=r"(a0), "=r"(a1), "=r"(a2), "=r"(a3)
                   : "r"(snt + 32 * i) : "memory");
      mma16<false>(&rs[i][0], a0, a1, a2, a3, tb[0], tb[1]);
      mma16<false>(&rs[i][4], a0, a1, a2, a3, tb[2], tb[3]);
    }
    CK(3);
    const uint32_t tag16 = tag_of(upin(ep0) + 1), tag1 = tag16 & 1;
    {
      int it = 0;
#pragma unroll 1
      while (true) {
        uint32_t bad = 0;
#pragma unroll
        for (int i = 0; i < 3; i++) bad |= diff2(ms[i].x, ms[i].y, tag16) | diff2(mc[i].x, mc[i].y, tag16);
        if (!any(bad & 0xffffu) || ++it > SPIN_MAX) break;
        load_mod();
      }
      CK(4);
      if (tid == 0) TS(3);
#pragma unroll
      for (int i = 0; i < 3; i++) {
        const float c0 = bf_hi(mc[i].x), c1 = bf_hi(mc[i].y);
        const float s0 = __uint_as_float(ms[i].x & smask), s1 = __uint_as_float(ms[i].y & smask);
        stmatrix4(sb1[i], pack_bf16(fmaf(rs[i][0], c0, s0), rs[i][1] * c0), pack_bf16(fmaf(rs[i][2], c1, s1), rs[i][3] * c1),
                  pack_bf16(rs[i][4] * c0, rs[i][5] * c0), pack_bf16(rs[i][6] * c1, rs[i][7] * c1));
      }
    }
    fence_async_smem();
    CK(5);
    if (wg == 2) {
      bar_arrive(5, NTHR);
      if (R >= 0 && elect()) load_filter(wp - 8);
      __syncwarp();
      const int slot = 4 * (cta & 7) + ((cta >> 4) & 3) + 32 * (2 * (cta >> 6) + ((cta >> 3) & 1));
      const uint32_t c0 = upin(40 * slot), c1 = upin(60 * (wp & 1)), src = upin(sbase + O_Z1 + (wp & 1) * 9600);
      const CUtensorMap* mz = upin(&maps.z1);
      unsigned* hint = pin(sc->cnt + C_Z1 + 32 * (wp & 1));
      if (wp < 10) {
        bar_sync(2 + (wp & 1), 160);
        if (elect()) tma_st2d(mz, src, c0, c1);
        pause(HD1);
        if (elect()) red_add(hint, 1);
        bulk_commit_wait();
        if (tid == 256) TS(4);
        __syncwarp();
      }
    } else {
      bar_sync(5, NTHR);
      CK(6);
      float acc[36];
      const uint32_t db = (((sbase + O_B1 + wg * 9216) & 0x3FFFF) >> 4) | ((128 >> 4) << 16);
      wg_fence();
#pragma unroll
      for (int kk = 0; kk < 4; kk++) wgmma_rs_72(acc, af[kk].x, af[kk].y, af[kk].z, af[kk].w, db + kk * 16, 1024 >> 4, kk);
      wg_commit();
      wg_wait<0>();
      reg_fence(acc);
      CK(7);
      float2 za[9], zb[9];
#pragma unroll
      for (int i = 0; i < 9; i++) { za[i] = make_float2(acc[4 * i], acc[4 * i + 2]); zb[i] = make_float2(acc[4 * i + 1], acc[4 * i + 3]); }
      dft9(za); dft9(zb);
      if ((wp & 3) == wg) {
        const float sp = g ? 0.f : 1.f;
#pragma unroll
        for (int k = 1; k < 5; k++) {
          float2 a = za[k], b = za[9 - k];
          za[k] = make_float2(fmaf(sp, b.x, a.x), fmaf(-sp, b.y, a.y)); za[9 - k] = make_float2(fmaf(-sp, a.x, b.x), fmaf(sp, a.y, b.y));
          a = zb[k]; b = zb[9 - k];
          zb[k] = make_float2(fmaf(sp, b.x, a.x), fmaf(-sp, b.y, a.y)); zb[9 - k] = make_float2(fmaf(-sp, a.x, b.x), fmaf(sp, a.y, b.y));
        }
        const uint32_t w0 = set_tag(pack_bf16(za[0].y, 0.f), tag1), w1 = pack_bf16(zb[0].y, 0.f);
        asm volatile("{\n.reg .pred p;\nsetp.eq.u32 p, %3, 0;\n@p st.shared.v2.b32 [%0], {%1,%2};\n}" ::"r"(lo[0] + 288 * 8), "r"(w0), "r"(w1), "r"(g) : "memory");
        za[0].y = g ? za[0].y : 0.f; zb[0].y = g ? zb[0].y : 0.f;
      }
#pragma unroll
      for (int k1 = 0; k1 < 9; k1++) sts2(lo[k1], set_tag(pack_bf16(za[k1].x, za[k1].y), tag1), pack_bf16(zb[k1].x, zb[k1].y));
      fence_async_smem();
      CK(8);
      bar_arrive(2 + wg, 160);
      {
        const uint32_t fx = (((cta >> 4) ^ cta) & 3) << 3, dl = O_IN - O_Z1, st = sbase + O_ST + 15360 + tid * 16;
        sts4(st, (lo[0] ^ fx) + dl, (lo[1] ^ fx) + dl, (lo[2] ^ fx) + dl, (lo[3] ^ fx) + dl);
        sts4(st + 4096, (lo[4] ^ fx) + dl, (lo[5] ^ fx) + dl, (lo[6] ^ fx) + dl, (lo[7] ^ fx) + dl);
        sts4(st + 8192, (lo[8] ^ fx) + dl, (lo[0] ^ fx) + dl + (kap ? 0 : 288 * 8),
             sbase + O_B3 + wg * 1024 + (l >> 4) * 2048 + (2 * (kap & 24) + (l & 15)) * 16, 0);
      }
    }
    {
      uint32_t sy[6];
#pragma unroll
      for (int i = 0; i < 6; i++) {
        const int rr = 16 * (wp & 3) + g + 8 * (i & 1);
        sy[i] = sbase + O_Y + (t * 584 + 64 * ((3 * wg + (i >> 1) + 63 - rr) % 9) + rr) * 4;
      }
      sts4(sbase + O_ST + tid * 16, movm(tb[0]), movm(tb[2]), movm(tb[1]), movm(tb[3]));
      sts4(sbase + O_ST + 6144 + tid * 16, sy[0], sy[1], sy[2], sy[3]);
      sts2(sbase + O_ST + 12288 + tid * 8, sy[4], sy[5]);
    }
  } else {
    __syncthreads();
  }

  const unsigned ep = upin(lds(full0 + 248));
  const uint32_t tag16 = tag_of(ep), tag1 = ep & 1;
  auto load_wm = [&](int u) {
    if (wp > 8 && elect()) {
      mbar_expect(full0 + 8 * B_WM, 6144);
      tma2d(sbase + O_NRM + (wp - 9) * 6144, &maps.wm, 16 * u, 192 * (wp - 9), full0 + 8 * B_WM);
    }
    __syncwarp();
  };
  if (R >= 0) {
    const int nl = (col0 + wp < DF_) + (wg < 2 && col0 + wp + 12 < DF_);
    uint4 cf[2][4], G[4];
#pragma unroll
    for (int i = 0; i < 4; i++) {
      cf[0][i] = __ldg(p.tab + TB_P2 + i * 32 + l);
      cf[1][i] = __ldg(p.tab + TB_P2 + (pi ? i : 4 + i) * 32 + l);
      G[i] = __ldg(p.tab + TB_P2 + (8 + i) * 32 + l);
    }
    const uint32_t* zin = sc->z1 + (size_t)R * 5120;
    if (wp == 10) {
      const uint32_t* zu = upin(zin);
      if (elect()) mbar_expect(full0 + 8 * B_Z1, 20480);
      wait_cnt(sc->cnt + C_Z1 + 32 * (pi >> 2), 128 * ep - 40 * STRESS);
      if (elect()) {
        bulk_ld(sbase + O_P2, zu, 20480, full0 + 8 * B_Z1);
        TS(12);
      }
      __syncwarp();
    }
    mbar_wait(full0 + 8 * B_FLT, 0);
    CK(9);
    float wn[16], wc[16];
#pragma unroll 1
    for (int ln = nl - 1; ln >= 0; ln--) {
      const int col = col0 + wp + 12 * ln, k2 = (57 * col) & 63;
      const bool cj = k2 > 32;
      const float nr = ((col & 31) == 0 && col != 0 && col != 288 ? 0.5f : 1.0f) / ((float)S_ * D_), ni = cj ? -nr : nr;
#pragma unroll
      for (int i = 0; i < 16; i++) wn[i] = wc[i];
#pragma unroll
      for (int cl = 0; cl < 2; cl++) {
        const int v = cl ^ (cj && pi), e = ((v ? xv : xu) & 15) + wp + 12 * ln, sh = e < 32 ? 6 : 5;
        const uint32_t base = sbase + O_RAW + v * 12288 + (e < 32 ? 2 * e : 8192 - 64 + 2 * e), msk = e < 32 ? 0x30 : 0x10;
        const int dm = v ? (cj || pi ? -1 : 0) : 0;
#pragma unroll
        for (int tt = 0; tt < 4; tt++) {
          const int kc = g + 64 * (tt >> 1) + 16 * t + 8 * (tt & 1);
          uint32_t a = base + ((((cj ? -kc : kc) + dm) & 127) << sh);
          a ^= (a >> 3) & msk;
          wc[4 * tt + 2 * cl] = lds_bf(a) * nr; wc[4 * tt + 2 * cl + 1] = lds_bf(a + 24576) * ni;
        }
      }
    }
    const float al = __uint_as_float(pin((pi ? 0x3f800000u : 0u) + (l >> 5)));
    const uint32_t tagv = pin(tag1 + (l >> 5));
    CK(10);
    uint32_t off = pin(l * 160 + ((wp ^ (g & 3)) << 3));
    uint32_t offo = pin(sbase + O_P2 + 20480 + off - 64 * l), po = 3072;
    unsigned* hz2 = pin(sc->cnt + C_Z2);
    const uint32_t do2 = pin(12288 - 32 * l);
    const CUtensorMap* mz2 = upin(&maps.z2[wp == 0]);
    const uint32_t sz2 = upin(sbase + O_P2 + 20480 + (wp ? 0 : 12288)), cz2 = upin(40 * R + (wp ? 0 : 24));
    mbar_wait(full0 + 8 * B_Z1, 0);
    CK(11);
    if (tid == 0) TS(8);
    if (wg == 2) load_wm(72 + mu);
    uint2 v[4], v2[4];
    const uint32_t o2 = nl > 1 ? 96 : 0;
#pragma unroll
    for (int i = 0; i < 4; i++) { v[i] = lds2(sbase + O_P2 + off + i * 5120); v2[i] = lds2(sbase + O_P2 + off + o2 + i * 5120); }
    auto bad2 = [&]() {
      return any(or3(or3(diff2(v[0].x, v[1].x, tagv), diff2(v[2].x, v[3].x, tagv), diff2(v2[0].x, v2[1].x, tagv)), diff2(v2[2].x, v2[3].x, tagv), 0) & 1);
    };
    if (__builtin_expect(bad2() && nl, 0)) {
      FAILCNT(0);
      int it = 0;
      do {
#pragma unroll
        for (int i = 0; i < 4; i++) {
          v[i] = ld_rlx2(reinterpret_cast<const uint8_t*>(zin) + off + i * 5120);
          v2[i] = ld_rlx2(reinterpret_cast<const uint8_t*>(zin) + off + o2 + i * 5120);
        }
      } while (bad2() && ++it < SPIN_MAX);
    }
#pragma unroll 1
    for (int ln = 0; ln < nl; ln++, offo += do2, po = 2048) {
      float d[4][4];
      uint32_t A[8];
#pragma unroll
      for (int h = 0; h < 2; h++) {
        mma16<false>(d[2 * h], cf[0][0].x, cf[0][0].y, cf[0][0].z, cf[0][0].w, v[h].x, v[2 + h].x);
        mma16<false>(d[2 * h + 1], cf[1][0].x, cf[1][0].y, cf[1][0].z, cf[1][0].w, v[h].y, v[2 + h].y);
      }
      if (ln) { fence_async_smem(); bar_arrive(15, NTHR); }
#pragma unroll
      for (int h = 0; h < 2; h++)
#pragma unroll
        for (int L = 0; L < 2; L++) {
          const uint4 tw = cf[L][2 + h];
          const float* z = d[2 * h + L];
          const float2 z0 = cmul(make_float2(z[0], z[2]), make_float2(__uint_as_float(tw.x), __uint_as_float(tw.y)));
          const float2 z1 = cmul(make_float2(z[1], z[3]), make_float2(__uint_as_float(tw.z), __uint_as_float(tw.w)));
          A[4 * h + L] = pack_bf16(z0.x, z0.y); A[4 * h + 2 + L] = pack_bf16(z1.x, z1.y);
        }
#pragma unroll
      for (int tt = 0; tt < 4; tt++) {
        mma16<false>(d[tt], A[0], A[1], A[2], A[3], G[tt].x, G[tt].y);
        mma16<true>(d[tt], A[4], A[5], A[6], A[7], G[tt].z, G[tt].w);
      }
#pragma unroll
      for (int tt = 0; tt < 4; tt++) {
        const float ar = d[tt][0], aj = d[tt][1], br = d[tt][2], bj = d[tt][3];
        const float2 y1 = cmul(make_float2(fmaf(-al, bj, ar), fmaf(al, br, aj)), make_float2(wc[4 * tt], wc[4 * tt + 1]));
        const float2 y2 = cmul(make_float2(fmaf(al, ar, bj), fmaf(al, aj, -br)), make_float2(wc[4 * tt + 2], wc[4 * tt + 3]));
        A[2 * tt] = pack_bf16(fmaf(al, y2.x, y1.x), fmaf(-al, y2.y, -y1.y));
        A[2 * tt + 1] = pack_bf16(fmaf(al, y1.y, -y2.y), fmaf(al, y1.x, -y2.x));
      }
#pragma unroll
      for (int i = 0; i < 16; i++) wc[i] = wn[i];
#pragma unroll
      for (int i = 0; i < 4; i++) v[i] = v2[i];
#pragma unroll
      for (int tt = 0; tt < 4; tt++) {
        mma16<false>(d[tt], A[0], A[1], A[2], A[3], G[tt].x, G[tt].y);
        mma16<true>(d[tt], A[4], A[5], A[6], A[7], G[tt].z, G[tt].w);
      }
#pragma unroll
      for (int h = 0; h < 2; h++)
#pragma unroll
        for (int L = 0; L < 2; L++) {
          const uint4 tw = cf[L][2 + h];
          const float2 z0 = cmul(make_float2(d[2 * h][2 * L], d[2 * h][2 * L + 1]), make_float2(__uint_as_float(tw.x), __uint_as_float(tw.y)));
          const float2 z1 = cmul(make_float2(d[2 * h + 1][2 * L], d[2 * h + 1][2 * L + 1]), make_float2(__uint_as_float(tw.z), __uint_as_float(tw.w)));
          A[4 * h + 2 * L] = movm(pack_bf16(z0.x, z1.x)); A[4 * h + 2 * L + 1] = movm(pack_bf16(z0.y, z1.y));
        }
#pragma unroll
      for (int h = 0; h < 2; h++) {
        mma16<false>(d[0], cf[0][1].x, cf[0][1].y, cf[0][1].z, cf[0][1].w, A[4 * h], A[4 * h + 1]);
        mma16<false>(d[1], cf[1][1].x, cf[1][1].y, cf[1][1].z, cf[1][1].w, A[4 * h + 2], A[4 * h + 3]);
#pragma unroll
        for (int e = 0; e < 2; e++)
          sts2(offo + (2 * h + e) * po, set_tag(pack_bf16(d[0][e], d[0][2 + e]), tagv), pack_bf16(d[1][e], d[1][2 + e]));
      }
      CK(12 + ln);
    }
    if (tid == 0) TS(1);
    fence_async_smem();
    if (nl < 2 && wp != 8) bar_arrive(15, NTHR);
    if (wp) bar_arrive(6, NTHR);
    if (!(wp & 7)) {
      bar_sync(wp ? 15 : 6, NTHR);
      if (elect()) tma_st2d(mz2, sz2, cz2, 0);
      if (wp == 0 && elect()) red_add(hz2, 1);
      if (tid == 0) TS(9);
      if (wp == 0) bulk_commit_wait();
      __syncwarp();
    }
  }
  if (wg == 2) {
#pragma unroll 1
    for (int u = 72 + mu, k = 0; u < 216; u += NCTA, k ^= 1) {
      if (R < 0) { fence_async_smem(); bar_sync(4, 128); load_wm(u); }
      mod_unit(sc, u, t128, sbase + O_NRM, full0 + 8 * B_WM, k, red + 256 - 256 * k, tag16);
    }
    fence_async_smem();
    CK(13);
  }

  const int grp = bx / 11, m1 = bx - 11 * grp;
  const bool helper = (m1 & 3) == 3;
  const int f1 = 384 * grp + (helper ? 192 : 128) * (m1 >> 2);
  const int d1 = 160 * (m1 & 3), flip = m1 >= 7;
  const int a1bytes = helper ? 24576 : 16384;
  auto load_a1 = [&](int st, int kb) {
    mbar_expect(full0 + 8 * st, a1bytes);
    tma4d_ef(sbase + st * STAGE, helper ? &maps.w1b : &maps.w1a, 4 * (kb >> 3), 16 * (kb & 7), f1 >> 6, full0 + 8 * st);
  };

  uint32_t bia[4];
  if (wg < 2) {
    const int fa = f1 + (helper ? 128 : 64) * (wg ^ flip) + 16 * (wp & 3) + g, fb = helper ? f1 + 64 + 16 * (wp & 3) + g : fa;
#pragma unroll
    for (int i = 0; i < 4; i++) asm volatile("ld.global.nc.u16 %0, [%1];" : "=r"(bia[i]) : "l"(p.b1 + (i < 2 ? fa : fb) + 8 * (i & 1)) : "memory");
  }
  if (rows) {
#pragma unroll
    for (int kk = 0; kk < 4; kk++) af[kk] = __ldg(p.tab + TB_E + kk * 128 + t128);
    const uint4 c0 = lds4(sbase + O_ST + tid * 16), c1 = lds4(sbase + O_ST + 6144 + tid * 16);
    const uint2 c2 = lds2(sbase + O_ST + 12288 + tid * 8);
    const uint32_t tc[4] = {c0.x, c0.y, c0.z, c0.w}, sy[6] = {c1.x, c1.y, c1.z, c1.w, c2.x, c2.y};
    const uint32_t l8 = pin(8 * l), syl = pin(sbase + O_Y + wp * 2336 + 8 * l);
    uint32_t sh3[3], ham[3];
#pragma unroll
    for (int k = 0; k < 3; k++) {
      const int pos = k && (l >> 4) == k - 1 ? 2 * (l & 6) + ((l >> 2) & 2) + (l & 1) : l & 15;
      const int sw = 2 * cta + ((wp >> 1) & 1), ph = pos ^ ((sw & 3) << 2);
      sh3[k] = pin((l >> 4) * 256 + (wp & 3) * 64 + ph * 4);
      ham[k] = pin(((ph ^ sw) & 7) == 0 ? ~1u : ~0u);
    }
    unsigned* const hh3 = upin(sc->cnt + C_H3 + (cta >> 4));
    uint8_t* const h3g = pin(sc->h3 + (cta >> 4) * (18 * 4096) + (cta & 15) * 256 + (l >> 4) * 3840);
    const int slot = 4 * (cta >> 4) + ((cta >> 1) & 3) + 32 * (2 * ((cta >> 3) & 1) + (cta & 1));
    const uint32_t* zin = sc->z2 + (size_t)slot * 4800;
    if (wg == 2) {
      {
        uint4 v[4];
        const int i3 = min(t128 + 384, 431);
        int it = 0;
        while (true) {
          uint32_t bad = 0;
#pragma unroll
          for (int k = 0; k < 4; k++) v[k] = ld_rlx4(sc->mod + 4 * (k < 3 ? t128 + 128 * k : i3));
#pragma unroll
          for (int k = 0; k < 4; k++) {
            v[k].x ^= tag16; v[k].y ^= tag16; v[k].z ^= tag16; v[k].w ^= tag16;
            bad |= v[k].x | v[k].y | v[k].z | v[k].w;
          }
          if (!any(bad & 0xffffu) || ++it > SPIN_MAX) break;
        }
#pragma unroll
        for (int k = 0; k < 4; k++) sts4(sbase + O_MOD + 16 * (k < 3 ? t128 + 128 * k : i3), v[k].x, v[k].y, v[k].z, v[k].w);
      }
      CK(14);
      bulk_commit_wait();
      bar_sync(10, NTHR);
      mbar_wait(full0 + 8 * B_Z2, 0);
      if (elect()) {
        load_a1(wp - 8, wp - 8);
      }
      __syncwarp();
    } else {
      const uint4 e0 = lds4(sbase + O_ST + 15360 + tid * 16), e1 = lds4(sbase + O_ST + 19456 + tid * 16), e2 = lds4(sbase + O_ST + 23552 + tid * 16);
      const uint32_t li[9] = {e0.x, e0.y, e0.z, e0.w, e1.x, e1.y, e1.z, e1.w, e2.x}, lx = e2.y, sb3 = e2.z;
      bar_arrive(10, NTHR);
      CK(14);
      if (wp == 1) {
        const uint32_t* zu = upin(zin);
        if (elect()) mbar_expect(full0 + 8 * B_Z2, 19200);
        wait_cnt(sc->cnt + C_Z2, 120 * ep - 40 * STRESS);
        if (elect()) {
          bulk_ld(sbase + O_IN, zu, 19200, full0 + 8 * B_Z2);
          TS(14);
        }
        __syncwarp();
      }
      mbar_wait(full0 + 8 * B_Z2, 0);
      CK(15);
      if (tid == 0) TS(11);
      uint2 v[10];
#pragma unroll
      for (int k1 = 0; k1 < 10; k1++) v[k1] = lds2(k1 < 9 ? li[k1] : lx);
      float2 za[9], zb[9];
      int it = 0;
#pragma unroll 1
      while (true) {
      const uint32_t bad = or3(or3(diff2(v[0].x, v[1].x, tag1), diff2(v[2].x, v[3].x, tag1), diff2(v[4].x, v[5].x, tag1)), diff2(v[6].x, v[7].x, tag1), diff2(v[8].x, v[9].x, tag1));
#pragma unroll
      for (int i = 0; i < 9; i++) { za[i] = make_float2(bf_lo(v[i].x), bf_hi(v[i].x)); zb[i] = make_float2(bf_lo(v[i].y), bf_hi(v[i].y)); }
      if ((wp & 3) == wg) {
        const float sp = g ? 0.f : 1.f;
#pragma unroll
        for (int k = 1; k < 5; k++) {
          float2 a = za[k], b = za[9 - k];
          za[k] = make_float2(fmaf(-sp, b.x, a.x), fmaf(sp, b.y, a.y)); za[9 - k] = make_float2(fmaf(sp, a.x, b.x), fmaf(-sp, a.y, b.y));
          a = zb[k]; b = zb[9 - k];
          zb[k] = make_float2(fmaf(-sp, b.x, a.x), fmaf(sp, b.y, a.y)); zb[9 - k] = make_float2(fmaf(sp, a.x, b.x), fmaf(-sp, a.y, b.y));
        }
        za[0].y = g ? za[0].y : bf_lo(v[9].x); zb[0].y = g ? zb[0].y : bf_lo(v[9].y);
      }
      dft9(za); dft9(zb);
#pragma unroll
      for (int n = 0; n < 8; n += 2) {
        const int i0 = (9 - n) % 9, i1 = 8 - n;
        stmatrix4(sb3 + n * 2048, pack_bf16(za[i0].x, zb[i0].x), pack_bf16(za[i0].y, zb[i0].y), pack_bf16(za[i1].x, zb[i1].x), pack_bf16(za[i1].y, zb[i1].y));
      }
      stmatrix2(sb3 + 8 * 2048, pack_bf16(za[1].x, zb[1].x), pack_bf16(za[1].y, zb[1].y));
      if (__builtin_expect(!any(bad & 1) || ++it > SPIN_MAX, 1)) break;
      FAILCNT(1);
#pragma unroll
      for (int k1 = 0; k1 < 10; k1++) v[k1] = ld_rlx2(reinterpret_cast<const uint8_t*>(zin) + (pin(k1 < 9 ? li[k1] : lx) - (sbase + O_IN)));
      }
      fence_async_smem();
    }
    CK(16);
    __syncthreads();
    CK(17);
    float acc[24];
    const uint32_t db = (((sbase + O_B3 + wg * 6144) & 0x3FFFF) >> 4) | ((128 >> 4) << 16);
    wg_fence();
#pragma unroll
    for (int kk = 0; kk < 4; kk++) wgmma_rs_48(acc, af[kk].x, af[kk].y, af[kk].z, af[kk].w, db + kk * 16, 1024 >> 4, kk);
    wg_commit();
    uint32_t ga[9];
    if (wg < 2) {
#pragma unroll
      for (int i = 0; i < 9; i++) { const uint2 v = lds2(l8 + sbase + O_MOD + 256 * i); ga[i] = __byte_perm(v.x, v.y, 0x7632); }
    }
    wg_wait<0>();
    reg_fence(acc);
    CK(18);
#pragma unroll
    for (int i = 0; i < 3; i++) {
      const float* a = &acc[8 * i];
      const uint32_t a0 = pack_bf16(a[0], a[1]), a1 = pack_bf16(a[2], a[3]), a2 = pack_bf16(a[4], a[5]), a3 = pack_bf16(a[6], a[7]);
#pragma unroll
      for (int jh = 0; jh < 2; jh++) {
        float y[4];
        mma16<false>(y, a0, a1, a2, a3, tc[2 * jh], tc[2 * jh + 1]);
        sts(sy[2 * i] + jh * (4 * 584 * 4), pack_bf16(y[0], y[1]));
        sts(sy[2 * i + 1] + jh * (4 * 584 * 4), pack_bf16(y[2], y[3]));
      }
    }
    CK(19);
    if (wg == 2) bar_arrive(7, NTHR); else bar_sync(7, NTHR);
    if (wg) bar_sync(15, NTHR);
    if (wg < 2) {
      CK(20);
      uint2 y[9], sh[9], sw[9];
#pragma unroll
      for (int i = 0; i < 9; i++) y[i] = lds2(syl + 256 * i);
      uint32_t sel = 0x5410, sto = sbase + O_B3 + wg * 9216;
#pragma unroll 1
      for (int e = 0; e < 2; e++, sel = 0x7632, sto += 4608) {
        float a[18];
#pragma unroll
        for (int i = 0; i < 9; i++) {
          const uint32_t x1 = hfma2(ga[i], __byte_perm(y[i].x, y[i].y, sel), xr[i]);
          xr[i] = xr[9 + i]; xr[9 + i] = x1;
          a[2 * i] = bf_lo(x1); a[2 * i + 1] = bf_hi(x1);
        }
#pragma unroll
        for (int i = 0; i < 9; i++) { lds2_if(!e, sh[i], l8 + sbase + O_MOD + 4 * D_ + 256 * i); lds2_if(!e, sw[i], l8 + sbase + O_MOD + 8 * D_ + 256 * i); }
        float oa, ra;
        ln_stats1(a, 1.0f, oa, ra);
#pragma unroll
        for (int i = 0; i < 9; i++) {
          a[2 * i] = fmaf(fmaf(a[2 * i], ra, oa), __uint_as_float(sw[i].x), __uint_as_float(sh[i].x));
          a[2 * i + 1] = fmaf(fmaf(a[2 * i + 1], ra, oa), __uint_as_float(sw[i].y), __uint_as_float(sh[i].y));
        }
        ln_stats1(a, 0.5f, oa, ra);
        uint32_t hv[9];
#pragma unroll
        for (int i = 0; i < 9; i++) hv[i] = bitsel(pack_bf16(fmaf(a[2 * i], ra, oa), fmaf(a[2 * i + 1], ra, oa)), ham[i == 2 ? 1 : i == 6 ? 2 : 0], tag1);
        if (!(wg | e)) {
          if (elect()) red_add(hh3, 1);
#pragma unroll
          for (int i = 0; i < 9; i++) asm volatile("st.global.b32 [%0], %1;" ::"l"(h3g + sh3[i == 2 ? 1 : i == 6 ? 2 : 0] + i * 8192), "r"(hv[i]) : "memory");
          bar_arrive(15, NTHR);
          if (tid == 0) TS(13);
        } else {
#pragma unroll
          for (int i = 0; i < 9; i++) sts(sto + sh3[i == 2 ? 1 : i == 6 ? 2 : 0] + i * 512, hv[i]);
        }
        if (!e) bar_arrive(8, 288);
        CK(21 + e);
      }
      fence_async_smem();
      bar_arrive(9, 288);
      CK(23);
    }
  }

  const bool g2 = rows;
  const int z2 = cta, r = z2 >> 6;
  const int s2 = 128 * ((z2 >> 2) & 15), d2 = 144 * (z2 & 3);
  constexpr int ST0 = 32 % NST;
  const bool first = helper || m1 < W0N;

  if (wg == 2) {
    asm volatile("setmaxnreg.dec.sync.aligned.u32 40;");
    const int l = lane_id(), g = l >> 2;
    auto load_b = [&](bool second, int i, int st) {
      const uint32_t lb = full0 + 8 * (B_LAND + st), bytes = second ? 18432 : STAGE - a1bytes;
      mbar_expect(lb, bytes);
      bulk_ld(sbase + (second ? st * STAGE2 + 16384 : st * STAGE + a1bytes),
              second ? sc->u + ((size_t)(36 * r + kb2_order(i)) * D_ + d2) * 128 : sc->h3 + ((size_t)(i * 18 + (d1 >> 5)) << 12), bytes, lb);
    };
    if (wp == 8) {
      int st = rows ? 4 : 0, ph = 1;
#pragma unroll 1
      for (int kb = st; kb < 32; kb++) {
        if (rows && (kb >> 1) == 2) mbar_wait(full0 + 8 * (B_S4 - 4 + kb), 0);
        mbar_wait(empty0 + 8 * st, ph);
        if (elect()) {
          load_a1(st, kb);
        }
        __syncwarp();
        ring_next<false>(st, ph);
      }
      if (g2) {
        st++;
#pragma unroll 1
        for (int i = 0; i < 36; i++) {
          if (i == HOLDA) mbar_wait(full0 + 8 * B_GO, 0);
          mbar_wait(empty0 + 8 * st, ph);
          if (elect()) {
            mbar_expect(full0 + 8 * st, 16384);
            tma3d_ef(sbase + st * STAGE2, &maps.w2, 64 * (36 * r + kb2_order(i)), s2 >> 6, full0 + 8 * st);
          }
          __syncwarp();
          ring_next<true>(st, ph);
        }
      }
    } else if (wp >= 10) {
      const int sw = wp - 10;
      if (sw) {
        if (rows) {
          bar_sync(8, 288);
          mbar_wait(full0 + 8 * H3W, 0);
          if (elect()) mbar_arrive(full0 + 8 * B_S4);
          bar_sync(9, 288);
          if (elect()) tma_st3d(&maps.h3, sbase + O_B3 + 4608, 64 * (cta & 15), 18 * (cta >> 4), 1);
          bulk_commit_wait();
          if (elect()) {
            red_add(sc->cnt + C_H3 + (cta >> 4) + 8, 4);
            mbar_arrive(full0 + 8 * B_S5);
            TS(24);
            asm volatile("fence.acq_rel.gpu;" ::: "memory");
            red_add(&sc->cnt[C_X + 64], 1);
          }
          __syncwarp();
        }
        if (g2) {
          uint2 v[3];
          int it = 0;
          do {
#pragma unroll
            for (int i = 0; i < 3; i++) v[i] = ld_rlx2(sc->mod + 3 * D_ + d2 + 2 * min(l + 32 * i, 71));
          } while (any(or3(diff2(v[0].x, v[0].y, tag16), diff2(v[1].x, v[1].y, tag16), diff2(v[2].x, v[2].y, tag16)) & 0xffffu) && ++it < SPIN_MAX);
#pragma unroll
          for (int i = 0; i < 3; i++) sts(sbase + O_GB + 4 * min(l + 32 * i, 71), __byte_perm(v[i].x, v[i].y, 0x7632));
          __syncwarp();
        }
        wait_cnt<true>(&sc->cnt[C_X + 64], 128 * ep);
        if (elect()) mbar_arrive(full0 + 8 * B_X);
        __syncwarp();
      }
      uint32_t lph = 0;
      auto check_tiles = [&](bool second, int n, int st, uint32_t o1, uint32_t d2nd) {
        const uint32_t b1 = pin(sbase + o1), b2 = pin(sbase + o1 + d2nd);
        int i = 0, it = 0;
#pragma unroll 1
        do {
          const uint32_t so = st * (second ? STAGE2 : STAGE);
          mbar_wait(full0 + 8 * (B_LAND + st), (lph >> st) & 1);
          lph ^= 1u << st;
          uint32_t v[20];
#pragma unroll
          for (int k = 0; k < 20; k++) if (!second || k < 10 || k >= 12) v[k] = lds(k < 12 ? b1 + so + k * 1024 : b2 + so + (k - 12) * 1024); else v[k] = tag1;
#pragma unroll
          for (int k = 0; k < 10; k++) v[k] = diff2(v[2 * k], v[2 * k + 1], tag1);
          const uint32_t bad = or3(or3(or3(v[0], v[1], v[2]), or3(v[3], v[4], v[5]), v[6]), v[7], or3(v[8], v[9], 0));
          if (__builtin_expect(any(bad & 1) && ++it < SPIN_MAX, 0)) {
            FAILCNT(2 + second);
            fence_async_smem();
            __syncwarp();
            if (elect()) load_b(second, i, st);
            __syncwarp();
            continue;
          }
          if (elect()) mbar_arrive(full0 + 8 * st);
          if (++st == NST) st = 0;
          i++;
        } while (i < n);
      };
      if (!sw) check_tiles(false, NV1, 0, a1bytes + l * 32 + (l >> 2) * 4, helper ? 4096 : 12288);
      if (sw) {
#pragma unroll 1
        for (int k = 0; k < 2; k++) {
          bar_sync(13 + k, 160);
          if (helper || (first && !k)) continue;
          const uint32_t stg = sbase + (k ? O_U1 : ST0 * STAGE);
          const int kb = (f1 >> 6) + (k ^ flip);
          uint8_t* const ug = sc->u + ((size_t)kb * D_ + d1) * 128;
          if (g2) mbar_wait(full0 + 8 * B_GO, 0);
          if (first) pause(10 * TRK0);
#pragma unroll 1
          for (int i = 0; i < 20480; i += 2048) {
            if (elect()) bulk_st(ug + i, stg + i, 2048);
            pause(k ? TRKC : TRK0);
          }
          if (elect()) red_add(sc->cnt + C_U + kb2_pos(kb), 4);
          bulk_commit_wait();
          if (elect()) { if (!k) mbar_arrive(empty0 + 8 * ST0); TS(k ? 23 : 17); }
          __syncwarp();
        }
        if (elect()) { asm volatile("fence.acq_rel.gpu;" ::: "memory"); red_add(&sc->cnt[C_X], 1); }
        __syncwarp();
      }
      if (g2) {
        if (!sw) check_tiles(true, NV2, 3, 16384 + l * 32 + g * 4, 10240);
        else {
          wait_cnt<true>(&sc->cnt[C_X], NCTA * ep);
          if (elect()) mbar_arrive(full0 + 8 * B_X);
          if (cta == 0) sc->cnt[C_EP + l] = ep;
          __syncwarp();
        }
      }
      __syncwarp();
    } else {
      uint32_t ready = 0;
      int st = 0, ph = 1;
#pragma unroll 1
      for (int kb = 0; kb < 32; kb++) {
        const uint8_t* src = upin(sc->h3 + ((size_t)(kb * 18 + (d1 >> 5)) << 12));
        const uint32_t dst = upin(sbase + st * STAGE + a1bytes), lb = full0 + 8 * ((kb < NV1 ? B_LAND : 0) + st);
        if (kb == NV1) { mbar_wait(full0 + 8 * B_X, 0); fence_async_glb(); ready = ~0u; }
        if (rows && (kb >> 1) == 2) mbar_wait(full0 + 8 * (B_S4 - 4 + kb), 0);
        mbar_wait(empty0 + 8 * st, ph);
        if (elect()) mbar_expect(lb, STAGE - a1bytes);
        wait_flags(sc->cnt + C_H3 + l, (kb & 7) + (kb < 8 ? 0 : 8), 64 * ep - 24 * STRESS, ready);
        if (elect()) bulk_ld(dst, src, STAGE - a1bytes, lb);
        ring_next<false>(st, ph);
      }
      if (g2) {
        ready = 0;
        st++;
#pragma unroll 1
        for (int i = 0; i < 36; i++) {
          const int kb = kb2_order(i);
          const uint8_t* src = upin(sc->u + ((size_t)(36 * r + kb) * D_ + d2) * 128);
          const uint32_t dst = upin(sbase + st * STAGE2 + 16384), lb = full0 + 8 * ((i < NV2 ? B_LAND : 0) + st);
          if (i == NV2) { mbar_wait(full0 + 8 * B_X, 1); fence_async_glb(); ready = ~0u; }
          mbar_wait(empty0 + 8 * st, ph);
          if (elect()) mbar_expect(lb, 18432);
          wait_flags(sc->cnt + C_U + 64 * r + l, i & 31, 16 * ep - 8 * STRESS, ready);
          if (elect()) {
            bulk_ld(dst, src, 18432, lb);
            if (i == GOAT) mbar_arrive(full0 + 8 * B_GO);
          }
          ring_next<true>(st, ph);
        }
      }
    }
  } else {
    asm volatile("setmaxnreg.inc.sync.aligned.u32 232;");
    const int wgu = wg;
    constexpr uint32_t sb4 = sbase >> 4;
    const int w = wp & 3;
    Ring rg = {0, 0};
    uint32_t* const x1p = p.out + (size_t)(cta + 128 * ((wp & 3) + 8 * wg)) * 288 + l;
    const int direct = helper || (first && !wg), kbA = (f1 >> 6) + (helper ? 2 : 1) * (wg ^ flip), kbB = (f1 >> 6) + 1;
    const uint32_t uo = (t >> 1) * 2048 + (16 * w + g) * 32 + (((t ^ (g >> 2)) & 1) << 4);
    const uint32_t ad = pin(sbase + (wg ? O_U1 : ST0 * STAGE) + uo);
    uint8_t* const ug0 = pin(sc->u + ((size_t)kbA * D_ + d1) * 128 + uo);
    const int ud1 = upin(helper ? (kbB - kbA) * (D_ * 128) - 3 * 4096 : 0);
    unsigned* const uh = pin(sc->cnt + C_U + kb2_pos(l ? kbB : kbA));
    const int eh = direct && !helper && !l;
    const bool utg = ((t ^ (g >> 2) ^ w) & 1) == 0;
    const uint32_t um0 = pin(utg && g < 4 ? ~1u : ~0u), um1 = pin(utg && g >= 4 ? ~1u : ~0u);
    float acc[96];
    constexpr uint32_t LA = (8192 >> 4) << 16, LB = (4096 >> 4) << 16;
    {
      const float a0 = 0.5f * bf_lo(pin(bia[0])), a1 = 0.5f * bf_lo(pin(bia[1])), b0 = 0.5f * bf_lo(pin(bia[2])), b1 = 0.5f * bf_lo(pin(bia[3]));
#pragma unroll
      for (int i = 0; i < 96; i++) acc[i] = i < 48 ? ((i & 2) ? a1 : a0) : ((i & 2) ? b1 : b0);
      reg_fence(acc);
    }
    if (!helper) gemm_main<0>(acc, sb4 + (wgu ^ flip) * 512 + LA, 0, sb4 + 1024 + LB, wgu, rg, rows, first ? NST : NST - 1, x1p, xr);
    else {
      float ac2[96];
#pragma unroll
      for (int i = 0; i < 96; i++) asm volatile("mov.b32 %0, %1;" : "=f"(ac2[i]) : "f"(acc[i]));
      gemm_main<1>(ac2, sb4 + (wgu ^ flip) * 1024 + LA, sb4 + 512 + LA, sb4 + 1536 + LB, wgu, rg, rows, NST - 1, x1p, xr);
#pragma unroll
      for (int i = 0; i < 96; i++) asm volatile("mov.b32 %0, %1;" : "=f"(acc[i]) : "f"(ac2[i]));
    }
    if (t128 == 0) { TS(wg ? 16 : 6); if (wg) TSC(5); }
    {
      float tp[2] = {0.f, 0.f};
#pragma unroll
      for (int j = 0; j < 12; j++) {
        const float* a = &acc[16 * (j >> 1) + 2 * (j & 1)];
        const float k3 = j < 2 ? GK3 : fmaf(tp[j & 1], 0.0f, GK3);
        uint32_t o[4];
#pragma unroll
        for (int e = 0; e < 4; e++) {
          const float h0 = a[4 * e], h1 = a[4 * e + 1];
          float z0 = h0 * fmaf(h0 * k3, h0, GK1), z1 = h1 * fmaf(h1 * k3, h1, GK1);
          asm("tanh.approx.f32 %0, %0;" : "+f"(z0));
          asm("tanh.approx.f32 %0, %0;" : "+f"(z1));
          if (e == GDEP) tp[j & 1] = z0;
          o[e] = pack_bf16(fmaf(h0, z0, h0), fmaf(h1, z1, h1));
          if ((e >> 1) == (j & 1)) o[e] = bitsel(o[e], (e & 1) ? um1 : um0, tag1);
        }
        if (EH && j == EH) asm volatile("{\n.reg .pred p;\nsetp.ne.u32 p, %1, 0;\n@p red.relaxed.gpu.global.add.u32 [%0], 1;\n}" ::"l"(uh), "r"(eh) : "memory");
        asm volatile("{\n.reg .pred p;\nsetp.ne.u32 p, %6, 0;\n@p st.global.v4.b32 [%0], {%2,%3,%4,%5};\n@!p st.shared.v4.b32 [%1], {%2,%3,%4,%5};\n}"
                     ::"l"(ug0 + (j < 6 ? 0 : ud1) + (j >> 1) * 4096 + (j & 1) * 256), "r"(ad + (j >> 1) * 4096 + (j & 1) * 256),
                       "r"(o[0]), "r"(o[1]), "r"(o[2]), "r"(o[3]), "r"(direct) : "memory");
        if ((j == 5 && helper && !wgu) || (j == 9 && !helper)) break;
      }
      if (!direct) fence_async_smem();
      else if (l <= wgu && (EH == 0 || helper)) red_add(uh, 1);
      __syncwarp();
      bar_arrive(13 + wgu, 160);
      if (t128 == 0) TS(wg ? 29 : 28);
    }
    if (g2) {
      const int mb = wgu ^ r;
      const int odd = z2 & 1;
      uint4 gq[4];
      uint2 gs;
      {
        float a0 = 0.f, a1 = 0.f;
        if (wgu) { a0 = __bfloat162float(p.b2[s2 + 64 * mb + 16 * w + g]); a1 = __bfloat162float(p.b2[s2 + 64 * mb + 16 * w + 8 + g]); }
#pragma unroll
        for (int i = 0; i < 4; i++) gq[i] = lds4(sbase + O_GB + 32 * odd + 64 * i + 16 * t);
        gs = lds2(sbase + O_GB + (odd ? 0 : 256) + 8 * t);
#pragma unroll
        for (int i = 0; i < 72; i++) acc[i] = (i & 2) ? a1 : a0;
      }
      uint32_t* const ob = p.out + (size_t)(s2 + 64 * mb + 16 * w + g) * 288 + (d2 >> 1);
      uint32_t* const oq = pin(ob + 8 * odd + 4 * t);
      uint32_t* const os = pin(ob + (odd ? 0 : 64) + 2 * t);
      rg.st++;
      gemm_main<3>(acc, sb4 + mb * 512 + LA, 0, sb4 + 1024 + ((2048 >> 4) << 16), wgu, rg, rows, NST, x1p, xr);
      if (t128 == 0) { TS(wg ? 20 : 19); if (wg) TSC(22); }
      auto finish = [&](const float* aq, const float* as) {
#pragma unroll
        for (int i = 0; i < 8; i++) {
          const float* a = aq + 16 * (i >> 1) + 2 * (i & 1);
          const uint4 gv = gq[i >> 1];
          red_bf16x8(oq + (i & 1) * 2304 + 16 * (i >> 1), hmul2(gv.x, pack_bf16(a[0], a[1])), hmul2(gv.y, pack_bf16(a[4], a[5])),
                     hmul2(gv.z, pack_bf16(a[8], a[9])), hmul2(gv.w, pack_bf16(a[12], a[13])));
        }
#pragma unroll
        for (int i = 0; i < 2; i++) red_bf16x4(os + i * 2304, hmul2(gs.x, pack_bf16(as[2 * i], as[2 * i + 1])), hmul2(gs.y, pack_bf16(as[2 * i + 4], as[2 * i + 5])));
      };
      if (odd) finish(&acc[8], &acc[0]); else finish(&acc[0], &acc[64]);
      if (t128 == 0) TS(wg ? 7 : 21);
      __syncwarp();
    }
  }
}

typedef CUresult (*EncodeFn)(CUtensorMap*, CUtensorMapDataType, cuuint32_t, void*, const cuuint64_t*, const cuuint64_t*, const cuuint32_t*,
                             const cuuint32_t*, CUtensorMapInterleave, CUtensorMapSwizzle, CUtensorMapL2promotion, CUtensorMapFloatOOBfill);

struct Dim { cuuint64_t n, stride; cuuint32_t box; };
template <int RANK>
void make_map(EncodeFn enc, CUtensorMap* m, bool words, int swz, const void* ptr, const Dim (&d)[RANK]) {
  cuuint64_t gd[RANK], gs[RANK];
  cuuint32_t bx[RANK], es[RANK];
  for (int i = 0; i < RANK; i++) { gd[i] = d[i].n; gs[i] = d[i].stride; bx[i] = d[i].box; es[i] = 1; }
  enc(m, words ? CU_TENSOR_MAP_DATA_TYPE_UINT32 : CU_TENSOR_MAP_DATA_TYPE_BFLOAT16, RANK, const_cast<void*>(ptr), gd, gs + 1, bx, es,
      CU_TENSOR_MAP_INTERLEAVE_NONE, static_cast<CUtensorMapSwizzle>(swz),
      swz == 3 ? CU_TENSOR_MAP_L2_PROMOTION_L2_256B : CU_TENSOR_MAP_L2_PROMOTION_NONE, CU_TENSOR_MAP_FLOAT_OOB_FILL_NONE);
}

}

extern "C" void kernel_launch(void* const* d_in, const int* in_sizes, int n_in, void* d_out, int out_size) {
  (void)in_sizes; (void)n_in; (void)out_size;
  static EncodeFn enc = nullptr;
  static void *sptr = nullptr, *tptr = nullptr;
  if (!enc) {
    void* f = nullptr; cudaDriverEntryPointQueryResult qr;
    cudaGetDriverEntryPoint("cuTensorMapEncodeTiled", &f, cudaEnableDefault, &qr);
    enc = reinterpret_cast<EncodeFn>(f);
    cudaFuncSetAttribute(fused_kernel, cudaFuncAttributeMaxDynamicSharedMemorySize, SMEM_BYTES);
    cudaGetSymbolAddress(&sptr, g_s);
    cudaGetSymbolAddress(&tptr, T_TAB);
  }
  Params p;
  p.x = (const __nv_bfloat16*)d_in[0]; p.wr = (const __nv_bfloat16*)d_in[1]; p.wi = (const __nv_bfloat16*)d_in[2];
  p.b1 = (const __nv_bfloat16*)d_in[5]; p.b2 = (const __nv_bfloat16*)d_in[7];
  p.c = (const __nv_bfloat16*)d_in[8]; p.wmod = (const __nv_bfloat16*)d_in[9];
  p.w1 = (const __nv_bfloat16*)d_in[4]; p.w2 = (const __nv_bfloat16*)d_in[6];
  p.out = static_cast<uint32_t*>(d_out); p.s = static_cast<Scratch*>(sptr); p.tab = static_cast<const uint4*>(tptr);
  Maps maps;
  make_map<4>(enc, &maps.w1a, false, 3, p.w1, {{64, 0, 64}, {16, 128 * 2 * F_, 4}, {128, 2 * F_, 16}, {72, 128, 2}});
  make_map<4>(enc, &maps.w1b, false, 3, p.w1, {{64, 0, 64}, {16, 128 * 2 * F_, 4}, {128, 2 * F_, 16}, {72, 128, 3}});
  make_map<3>(enc, &maps.w2, false, 3, p.w2, {{64, 0, 64}, {F_, 2 * S_, 64}, {32, 128, 2}});
  make_map<2>(enc, &maps.z1, true, 0, p.s->z1, {{5120, 0, 40}, {120, 20480, 60}});
  for (int i = 0; i < 2; i++) make_map<2>(enc, &maps.z2[i], true, 0, p.s->z2, {{4800, 0, i ? 16u : 24u}, {128, 19200, 128}});
  for (int i = 0; i < 4; i++) make_map<2>(enc, &maps.wf[i], false, 2 - (i & 1), (i & 2) ? p.wi : p.wr, {{16 * DF_, 0, (i & 1) ? 16u : 32u}, {128, 32 * DF_, 128}});
  make_map<2>(enc, &maps.wm, false, 1, p.wmod, {{6 * D_, 0, 16}, {D_, 12 * D_, 192}});
  make_map<3>(enc, &maps.h3, true, 0, p.s->h3, {{1024, 0, 64}, {144, 4096, 18}, {4, 144 * 4096, 3}});
  fused_kernel<<<NCTA, NTHR, SMEM_BYTES, cudaStreamPerThread>>>(p, maps);
}
```

```cpp
#include <cuda_runtime.h>
#include <cuda_bf16.h>
#include <cuda.h>
#include <stdint.h>

namespace {

constexpr int S_ = 2048, D_ = 576, DF_ = 289, F_ = 4608;
constexpr int NCTA = 132, NTHR = 384;
constexpr int STAGE = 36864, NST = 6;
constexpr int STAGE2 = 34816, O_U1 = NST * STAGE2, O_GB = O_U1 + 20480, SMEM_BYTES = 232448;
constexpr uint32_t sbase = 1024, red = sbase + NST * STAGE, full0 = sbase + SMEM_BYTES - 256, empty0 = full0 + 8 * NST;
constexpr int O_NRM = 0, O_B1 = 19456, O_Z1 = 38912, O_P2 = 59392, O_ST = 3 * STAGE;
constexpr int O_RAW = 4 * STAGE;
constexpr int O_IN = 4 * STAGE, O_Y = O_IN + 19456, O_B3 = O_IN + 38912, O_MOD = O_IN + 57344;

__device__ __align__(128) const uint32_t T_TAB[5632] = {
0x3f803f80,0xbf803f80,0x3f803f80,0xbf803f80,0x3f803f80,0xbf803f80,0x3f803f80,0xbf803f80,0x3f803f80,0xbf803f80,0x3f803f80,0xbf803f80,
0x3f803f80,0xbf803f80,0x3f803f80,0xbf803f80,0x3f7f3f80,0xbdc90000,0x3f223f35,0xbf46bf35,0x3f753f7b,0xbe95be48,0x3ef13f0e,0xbf62bf55,
0x3f623f6d,0xbef1bec4,0x3e953ec4,0xbf75bf6d,0x3f463f55,0xbf22bf0e,0x3dc93e48,0xbf7fbf7b,0x3f7b3f80,0xbe480000,0xbe480000,0xbf7bbf80,
0x3f553f6d,0xbf0ebec4,0xbf0ebec4,0xbf55bf6d,0x3f0e3f35,0xbf55bf35,0xbf55bf35,0xbf0ebf35,0x3e483ec4,0xbf7bbf6d,0xbf7bbf6d,0xbe48bec4,
0x3f753f80,0xbe950000,0xbf62bf35,0xbef1bf35,0x3f223f55,0xbf46bf0e,0xbf7fbf7b,0x3dc9be48,0x3dc93ec4,0xbf7fbf6d,0xbf46bf6d,0x3f223ec4,
0xbef1be48,0xbf62bf7b,0xbe95bf0e,0x3f753f55,0x3f6d3f80,0xbec40000,0xbf6dbf80,0x3ec40000,0x3ec43f35,0xbf6dbf35,0xbec4bf35,0x3f6d3f35,
0xbec40000,0xbf6dbf80,0x3ec40000,0x3f6d3f80,0xbf6dbf35,0xbec4bf35,0x3f6d3f35,0x3ec43f35,0x3f623f80,0xbef10000,0xbe95bf35,0x3f753f35,
0x3dc93f0e,0xbf7fbf55,0x3f223e48,0x3f463f7b,0xbf46bec4,0xbf22bf6d,0x3f7f3f6d,0xbdc93ec4,0xbf75bf7b,0x3e95be48,0x3ef13f55,0xbf62bf0e,
0x3f553f80,0xbf0e0000,0x3f0e0000,0x3f553f80,0xbe483ec4,0xbf7bbf6d,0x3f7b3f6d,0xbe483ec4,0xbf7bbf35,0xbe48bf35,0x3e483f35,0xbf7bbf35,
0xbf0ebf6d,0x3f553ec4,0xbf55bec4,0xbf0ebf6d,0x3f463f80,0xbf220000,0x3f7f3f35,0x3dc93f35,0xbef13e48,0xbf62bf7b,0x3e953f55,0xbf75bf0e,
0xbf75bf6d,0x3e95bec4,0xbf62bec4,0xbef1bf6d,0x3dc9bf0e,0x3f7f3f55,0xbf22bf7b,0x3f463e48,0x3f353f80,0xbf350000,0x3f353f80,0xbf350000,
0xbf350000,0xbf35bf80,0xbf350000,0xbf35bf80,0xbf35bf80,0x3f350000,0xbf35bf80,0x3f350000,0x3f350000,0x3f353f80,0x3f350000,0x3f353f80,
0x3f223f80,0xbf460000,0xbdc93f35,0xbf7fbf35,0xbf62be48,0xbef1bf7b,0xbf75bf55,0x3e95bf0e,0xbe95bf6d,0x3f753ec4,0x3ef1bec4,0x3f623f6d,
0x3f7f3f0e,0x3dc93f55,0x3f463f7b,0xbf223e48,0x3f0e3f80,0xbf550000,0xbf550000,0xbf0ebf80,0xbf7bbec4,0xbe48bf6d,0xbe48bf6d,0x3f7b3ec4,
0x3e48bf35,0x3f7b3f35,0x3f7b3f35,0xbe483f35,0x3f553f6d,0xbf0e3ec4,0xbf0e3ec4,0xbf55bf6d,0x3ef13f80,0xbf620000,0xbf75bf35,0x3e95bf35,
0xbf7fbf0e,0x3dc9bf55,0x3f46be48,0x3f223f7b,0x3f22bec4,0x3f463f6d,0x3dc93f6d,0xbf7fbec4,0x3e953f7b,0xbf75be48,0xbf62bf55,0x3ef1bf0e,
0x3ec43f80,0xbf6d0000,0xbec4bf80,0x3f6d0000,0xbf6dbf35,0x3ec4bf35,0x3f6d3f35,0xbec43f35,0x3f6d0000,0x3ec43f80,0xbf6d0000,0xbec4bf80,
0xbec43f35,0xbf6dbf35,0x3ec4bf35,0x3f6d3f35,0x3e953f80,0xbf750000,0x3ef1bf35,0x3f623f35,0xbf46bf55,0x3f22bf0e,0x3dc93f7b,0xbf7fbe48,
0x3f7f3ec4,0xbdc93f6d,0xbf22bf6d,0x3f46bec4,0xbf623e48,0xbef1bf7b,0x3f753f0e,0xbe953f55,0x3e483f80,0xbf7b0000,0x3f7b0000,0x3e483f80,
0xbf0ebf6d,0x3f55bec4,0xbf553ec4,0xbf0ebf6d,0x3f553f35,0xbf0e3f35,0x3f0ebf35,0x3f553f35,0xbf7bbec4,0x3e48bf6d,0xbe483f6d,0xbf7bbec4,
0x3dc93f80,0xbf7f0000,0x3f463f35,0xbf223f35,0xbe95bf7b,0x3f75be48,0xbf62bf0e,0x3ef1bf55,0x3ef13f6d,0xbf623ec4,0x3f753ec4,0xbe953f6d,
0xbf22bf55,0x3f46bf0e,0xbf7fbe48,0x3dc9bf7b,0x3f80,0xbf800000,0x3f80,0xbf800000,0xbf80,0x3f800000,0xbf80,0x3f800000,
0x3f80,0xbf800000,0x3f80,0xbf800000,0xbf80,0x3f800000,0xbf80,0x3f800000,0xbdc93f80,0xbf7f0000,0xbf463f35,0xbf22bf35,
0x3e95bf7b,0x3f753e48,0x3f62bf0e,0x3ef13f55,0xbef13f6d,0xbf62bec4,0xbf753ec4,0xbe95bf6d,0x3f22bf55,0x3f463f0e,0x3f7fbe48,0x3dc93f7b,
0xbe483f80,0xbf7b0000,0xbf7b0000,0x3e48bf80,0x3f0ebf6d,0x3f553ec4,0x3f553ec4,0xbf0e3f6d,0xbf553f35,0xbf0ebf35,0xbf0ebf35,0x3f55bf35,
0x3f7bbec4,0x3e483f6d,0x3e483f6d,0xbf7b3ec4,0xbe953f80,0xbf750000,0xbef1bf35,0x3f62bf35,0x3f46bf55,0x3f223f0e,0xbdc93f7b,0xbf7f3e48,
0xbf7f3ec4,0xbdc9bf6d,0x3f22bf6d,0x3f463ec4,0x3f623e48,0xbef13f7b,0xbf753f0e,0xbe95bf55,0xbec43f80,0xbf6d0000,0x3ec4bf80,0x3f6d0000,
0x3f6dbf35,0x3ec43f35,0xbf6d3f35,0xbec4bf35,0xbf6d0000,0x3ec4bf80,0x3f6d0000,0xbec43f80,0x3ec43f35,0xbf6d3f35,0xbec4bf35,0x3f6dbf35,
0xbef13f80,0xbf620000,0x3f75bf35,0x3e953f35,0x3f7fbf0e,0x3dc93f55,0xbf46be48,0x3f22bf7b,0xbf22bec4,0x3f46bf6d,0xbdc93f6d,0xbf7f3ec4,
0xbe953f7b,0xbf753e48,0x3f62bf55,0x3ef13f0e,0xbf0e3f80,0xbf550000,0x3f550000,0xbf0e3f80,0x3f7bbec4,0xbe483f6d,0x3e48bf6d,0x3f7bbec4,
0xbe48bf35,0x3f7bbf35,0xbf7b3f35,0xbe48bf35,0xbf553f6d,0xbf0ebec4,0x3f0e3ec4,0xbf553f6d,0xbf223f80,0xbf460000,0x3dc93f35,0xbf7f3f35,
0x3f62be48,0xbef13f7b,0x3f75bf55,0x3e953f0e,0x3e95bf6d,0x3f75bec4,0xbef1bec4,0x3f62bf6d,0xbf7f3f0e,0x3dc9bf55,0xbf463f7b,0xbf22be48,
0xbf353f80,0xbf350000,0xbf353f80,0xbf350000,0x3f350000,0xbf353f80,0x3f350000,0xbf353f80,0x3f35bf80,0x3f350000,0x3f35bf80,0x3f350000,
0xbf350000,0x3f35bf80,0xbf350000,0x3f35bf80,0xbf463f80,0xbf220000,0xbf7f3f35,0x3dc9bf35,0x3ef13e48,0xbf623f7b,0xbe953f55,0xbf753f0e,
0x3f75bf6d,0x3e953ec4,0x3f62bec4,0xbef13f6d,0xbdc9bf0e,0x3f7fbf55,0x3f22bf7b,0x3f46be48,0xbf553f80,0xbf0e0000,0xbf0e0000,0x3f55bf80,
0x3e483ec4,0xbf7b3f6d,0xbf7b3f6d,0xbe48bec4,0x3f7bbf35,0xbe483f35,0xbe483f35,0xbf7b3f35,0x3f0ebf6d,0x3f55bec4,0x3f55bec4,0xbf0e3f6d,
0xbf623f80,0xbef10000,0x3e95bf35,0x3f75bf35,0xbdc93f0e,0xbf7f3f55,0xbf223e48,0x3f46bf7b,0x3f46bec4,0xbf223f6d,0xbf7f3f6d,0xbdc9bec4,
0x3f75bf7b,0x3e953e48,0xbef13f55,0xbf623f0e,0xbf6d3f80,0xbec40000,0x3f6dbf80,0x3ec40000,0xbec43f35,0xbf6d3f35,0x3ec4bf35,0x3f6dbf35,
0x3ec40000,0xbf6d3f80,0xbec40000,0x3f6dbf80,0x3f6dbf35,0xbec43f35,0xbf6d3f35,0x3ec4bf35,0xbf753f80,0xbe950000,0x3f62bf35,0xbef13f35,
0xbf223f55,0xbf463f0e,0x3f7fbf7b,0x3dc93e48,0xbdc93ec4,0xbf7f3f6d,0x3f46bf6d,0x3f22bec4,0x3ef1be48,0xbf623f7b,0x3e95bf0e,0x3f75bf55,
0xbf7b3f80,0xbe480000,0x3e480000,0xbf7b3f80,0xbf553f6d,0xbf0e3ec4,0x3f0ebec4,0xbf553f6d,0xbf0e3f35,0xbf553f35,0x3f55bf35,0xbf0e3f35,
0xbe483ec4,0xbf7b3f6d,0x3f7bbf6d,0xbe483ec4,0xbf7f3f80,0xbdc90000,0xbf223f35,0xbf463f35,0xbf753f7b,0xbe953e48,0xbef13f0e,0xbf623f55,
0xbf623f6d,0xbef13ec4,0xbe953ec4,0xbf753f6d,0xbf463f55,0xbf223f0e,0xbdc93e48,0xbf7f3f7b,0x3f803f80,0xbf803f80,0x3f803f80,0xbf803f80,
0x3f803f80,0xbf803f80,0x3f803f80,0xbf803f80,0x3f803f80,0xbf803f80,0x3f803f80,0xbf803f80,0x3f803f80,0xbf803f80,0x3f803f80,0xbf803f80,
0xbdc90000,0xbf7fbf80,0xbf46bf35,0xbf22bf35,0xbe95be48,0xbf75bf7b,0xbf62bf55,0xbef1bf0e,0xbef1bec4,0xbf62bf6d,0xbf75bf6d,0xbe95bec4,
0xbf22bf0e,0xbf46bf55,0xbf7fbf7b,0xbdc9be48,0xbf7bbf80,0x3e480000,0x3e480000,0x3f7b3f80,0xbf55bf6d,0x3f0e3ec4,0x3f0e3ec4,0x3f553f6d,
0xbf0ebf35,0x3f553f35,0x3f553f35,0x3f0e3f35,0xbe48bec4,0x3f7b3f6d,0x3f7b3f6d,0x3e483ec4,0x3e950000,0x3f753f80,0x3ef13f35,0xbf62bf35,
0x3f463f0e,0x3f223f55,0xbdc93e48,0xbf7fbf7b,0x3f7f3f6d,0x3dc93ec4,0xbf22bec4,0xbf46bf6d,0x3f623f7b,0xbef1be48,0xbf75bf55,0xbe95bf0e,
0x3f6d3f80,0xbec40000,0xbf6dbf80,0x3ec40000,0x3ec43f35,0xbf6dbf35,0xbec4bf35,0x3f6d3f35,0xbec40000,0xbf6dbf80,0x3ec40000,0x3f6d3f80,
0xbf6dbf35,0xbec4bf35,0x3f6d3f35,0x3ec43f35,0xbef10000,0xbf62bf80,0x3f753f35,0x3e953f35,0xbf7fbf55,0xbdc9bf0e,0x3f463f7b,0xbf22be48,
0xbf22bf6d,0x3f463ec4,0xbdc93ec4,0xbf7fbf6d,0x3e95be48,0x3f753f7b,0xbf62bf0e,0xbef1bf55,0xbf55bf80,0x3f0e0000,0xbf0e0000,0xbf55bf80,
0x3e48bec4,0x3f7b3f6d,0xbf7bbf6d,0x3e48bec4,0x3f7b3f35,0x3e483f35,0xbe48bf35,0x3f7b3f35,0x3f0e3f6d,0xbf55bec4,0x3f553ec4,0x3f0e3f6d,
0x3f220000,0x3f463f80,0xbdc9bf35,0x3f7f3f35,0x3f623f7b,0xbef13e48,0x3f753f0e,0x3e953f55,0xbe953ec4,0xbf75bf6d,0x3ef13f6d,0xbf62bec4,
0xbf7fbf55,0x3dc9bf0e,0xbf46be48,0xbf22bf7b,0x3f353f80,0xbf350000,0x3f353f80,0xbf350000,0xbf350000,0xbf35bf80,0xbf350000,0xbf35bf80,
0xbf35bf80,0x3f350000,0xbf35bf80,0x3f350000,0x3f350000,0x3f353f80,0x3f350000,0x3f353f80,0xbf460000,0xbf22bf80,0xbf7fbf35,0x3dc9bf35,
0xbef1bf7b,0x3f623e48,0x3e95bf0e,0x3f753f55,0x3f753ec4,0x3e953f6d,0x3f623f6d,0xbef13ec4,0x3dc93f55,0xbf7fbf0e,0xbf223e48,0xbf46bf7b,
0xbf0ebf80,0x3f550000,0x3f550000,0x3f0e3f80,0x3f7b3ec4,0x3e483f6d,0x3e483f6d,0xbf7bbec4,0xbe483f35,0xbf7bbf35,0xbf7bbf35,0x3e48bf35,
0xbf55bf6d,0x3f0ebec4,0x3f0ebec4,0x3f553f6d,0x3f620000,0x3ef13f80,0xbe953f35,0xbf75bf35,0xbdc93f55,0xbf7fbf0e,0xbf22bf7b,0x3f46be48,
0xbf46bf6d,0x3f22bec4,0x3f7f3ec4,0x3dc93f6d,0x3f753e48,0x3e953f7b,0xbef13f0e,0xbf62bf55,0x3ec43f80,0xbf6d0000,0xbec4bf80,0x3f6d0000,
0xbf6dbf35,0x3ec4bf35,0x3f6d3f35,0xbec43f35,0x3f6d0000,0x3ec43f80,0xbf6d0000,0xbec4bf80,0xbec43f35,0xbf6dbf35,0x3ec4bf35,0x3f6d3f35,
0xbf750000,0xbe95bf80,0x3f623f35,0xbef13f35,0x3f22bf0e,0x3f463f55,0xbf7fbe48,0xbdc9bf7b,0xbdc93f6d,0xbf7fbec4,0x3f46bec4,0x3f223f6d,
0xbef1bf7b,0x3f62be48,0xbe953f55,0xbf75bf0e,0xbe48bf80,0x3f7b0000,0xbf7b0000,0xbe48bf80,0x3f0e3f6d,0xbf553ec4,0x3f55bec4,0x3f0e3f6d,
0xbf55bf35,0x3f0ebf35,0xbf0e3f35,0xbf55bf35,0x3f7b3ec4,0xbe483f6d,0x3e48bf6d,0x3f7b3ec4,0x3f7f0000,0x3dc93f80,0x3f22bf35,0x3f463f35,
0xbf753e48,0xbe95bf7b,0xbef13f55,0xbf62bf0e,0x3f62bec4,0x3ef13f6d,0x3e95bf6d,0x3f753ec4,0xbf463f0e,0xbf22bf55,0xbdc93f7b,0xbf7fbe48,
0x3f80,0xbf800000,0x3f80,0xbf800000,0xbf80,0x3f800000,0xbf80,0x3f800000,0x3f80,0xbf800000,0x3f80,0xbf800000,
0xbf80,0x3f800000,0xbf80,0x3f800000,0xbf7f0000,0x3dc9bf80,0xbf22bf35,0x3f46bf35,0x3f753e48,0xbe953f7b,0x3ef13f55,0xbf623f0e,
0xbf62bec4,0x3ef1bf6d,0xbe95bf6d,0x3f75bec4,0x3f463f0e,0xbf223f55,0x3dc93f7b,0xbf7f3e48,0x3e48bf80,0x3f7b0000,0x3f7b0000,0xbe483f80,
0xbf0e3f6d,0xbf55bec4,0xbf55bec4,0x3f0ebf6d,0x3f55bf35,0x3f0e3f35,0x3f0e3f35,0xbf553f35,0xbf7b3ec4,0xbe48bf6d,0xbe48bf6d,0x3f7bbec4,
0x3f750000,0xbe953f80,0xbf623f35,0xbef1bf35,0xbf22bf0e,0x3f46bf55,0x3f7fbe48,0xbdc93f7b,0x3dc93f6d,0xbf7f3ec4,0xbf46bec4,0x3f22bf6d,
0x3ef1bf7b,0x3f623e48,0x3e953f55,0xbf753f0e,0xbec43f80,0xbf6d0000,0x3ec4bf80,0x3f6d0000,0x3f6dbf35,0x3ec43f35,0xbf6d3f35,0xbec4bf35,
0xbf6d0000,0x3ec4bf80,0x3f6d0000,0xbec43f80,0x3ec43f35,0xbf6d3f35,0xbec4bf35,0x3f6dbf35,0xbf620000,0x3ef1bf80,0x3e953f35,0xbf753f35,
0x3dc93f55,0xbf7f3f0e,0x3f22bf7b,0x3f463e48,0x3f46bf6d,0x3f223ec4,0xbf7f3ec4,0x3dc9bf6d,0xbf753e48,0x3e95bf7b,0x3ef13f0e,0xbf623f55,
0x3f0ebf80,0x3f550000,0xbf550000,0x3f0ebf80,0xbf7b3ec4,0x3e48bf6d,0xbe483f6d,0xbf7b3ec4,0x3e483f35,0xbf7b3f35,0x3f7bbf35,0x3e483f35,
0x3f55bf6d,0x3f0e3ec4,0xbf0ebec4,0x3f55bf6d,0x3f460000,0xbf223f80,0x3f7fbf35,0x3dc93f35,0x3ef1bf7b,0x3f62be48,0xbe95bf0e,0x3f75bf55,
0xbf753ec4,0x3e95bf6d,0xbf623f6d,0xbef1bec4,0xbdc93f55,0xbf7f3f0e,0x3f223e48,0xbf463f7b,0xbf353f80,0xbf350000,0xbf353f80,0xbf350000,
0x3f350000,0xbf353f80,0x3f350000,0xbf353f80,0x3f35bf80,0x3f350000,0x3f35bf80,0x3f350000,0xbf350000,0x3f35bf80,0xbf350000,0x3f35bf80,
0xbf220000,0x3f46bf80,0x3dc9bf35,0x3f7fbf35,0xbf623f7b,0xbef1be48,0xbf753f0e,0x3e95bf55,0x3e953ec4,0xbf753f6d,0xbef13f6d,0xbf623ec4,
0x3f7fbf55,0x3dc93f0e,0x3f46be48,0xbf223f7b,0x3f55bf80,0x3f0e0000,0x3f0e0000,0xbf553f80,0xbe48bec4,0x3f7bbf6d,0x3f7bbf6d,0x3e483ec4,
0xbf7b3f35,0x3e48bf35,0x3e48bf35,0x3f7bbf35,0xbf0e3f6d,0xbf553ec4,0xbf553ec4,0x3f0ebf6d,0x3ef10000,0xbf623f80,0xbf753f35,0x3e95bf35,
0x3f7fbf55,0xbdc93f0e,0xbf463f7b,0xbf223e48,0x3f22bf6d,0x3f46bec4,0x3dc93ec4,0xbf7f3f6d,0xbe95be48,0x3f75bf7b,0x3f62bf0e,0xbef13f55,
0xbf6d3f80,0xbec40000,0x3f6dbf80,0x3ec40000,0xbec43f35,0xbf6d3f35,0x3ec4bf35,0x3f6dbf35,0x3ec40000,0xbf6d3f80,0xbec40000,0x3f6dbf80,
0x3f6dbf35,0xbec43f35,0xbf6d3f35,0x3ec4bf35,0xbe950000,0x3f75bf80,0xbef13f35,0xbf623f35,0xbf463f0e,0x3f22bf55,0x3dc93e48,0xbf7f3f7b,
0xbf7f3f6d,0x3dc9bec4,0x3f22bec4,0xbf463f6d,0xbf623f7b,0xbef13e48,0x3f75bf55,0xbe953f0e,0x3f7bbf80,0x3e480000,0xbe480000,0x3f7bbf80,
0x3f55bf6d,0x3f0ebec4,0xbf0e3ec4,0x3f55bf6d,0x3f0ebf35,0x3f55bf35,0xbf553f35,0x3f0ebf35,0x3e48bec4,0x3f7bbf6d,0xbf7b3f6d,0x3e48bec4,
0x3dc90000,0xbf7f3f80,0x3f46bf35,0xbf223f35,0x3e95be48,0xbf753f7b,0x3f62bf55,0xbef13f0e,0x3ef1bec4,0xbf623f6d,0x3f75bf6d,0xbe953ec4,
0x3f22bf0e,0xbf463f55,0x3f7fbf7b,0xbdc93e48,0x3f803f80,0xbf803f80,0x3f803f80,0xbf803f80,0x3f803f80,0xbf803f80,0x3f803f80,0xbf803f80,
0x3f803f80,0xbf803f80,0x3f803f80,0xbf803f80,0x3f803f80,0xbf803f80,0x3f803f80,0xbf803f80,0xbf7fbf80,0x3dc90000,0xbf22bf35,0x3f463f35,
0xbf75bf7b,0x3e953e48,0xbef1bf0e,0x3f623f55,0xbf62bf6d,0x3ef13ec4,0xbe95bec4,0x3f753f6d,0xbf46bf55,0x3f223f0e,0xbdc9be48,0x3f7f3f7b,
0x3f7b3f80,0xbe480000,0xbe480000,0xbf7bbf80,0x3f553f6d,0xbf0ebec4,0xbf0ebec4,0xbf55bf6d,0x3f0e3f35,0xbf55bf35,0xbf55bf35,0xbf0ebf35,
0x3e483ec4,0xbf7bbf6d,0xbf7bbf6d,0xbe48bec4,0xbf75bf80,0x3e950000,0x3f623f35,0x3ef13f35,0xbf22bf55,0x3f463f0e,0x3f7f3f7b,0xbdc93e48,
0xbdc9bec4,0x3f7f3f6d,0x3f463f6d,0xbf22bec4,0x3ef13e48,0x3f623f7b,0x3e953f0e,0xbf75bf55,0x3f6d3f80,0xbec40000,0xbf6dbf80,0x3ec40000,
0x3ec43f35,0xbf6dbf35,0xbec4bf35,0x3f6d3f35,0xbec40000,0xbf6dbf80,0x3ec40000,0x3f6d3f80,0xbf6dbf35,0xbec4bf35,0x3f6d3f35,0x3ec43f35,
0xbf62bf80,0x3ef10000,0x3e953f35,0xbf75bf35,0xbdc9bf0e,0x3f7f3f55,0xbf22be48,0xbf46bf7b,0x3f463ec4,0x3f223f6d,0xbf7fbf6d,0x3dc9bec4,
0x3f753f7b,0xbe953e48,0xbef1bf55,0x3f623f0e,0x3f553f80,0xbf0e0000,0x3f0e0000,0x3f553f80,0xbe483ec4,0xbf7bbf6d,0x3f7b3f6d,0xbe483ec4,
0xbf7bbf35,0xbe48bf35,0x3e483f35,0xbf7bbf35,0xbf0ebf6d,0x3f553ec4,0xbf55bec4,0xbf0ebf6d,0xbf46bf80,0x3f220000,0xbf7fbf35,0xbdc9bf35,
0x3ef1be48,0x3f623f7b,0xbe95bf55,0x3f753f0e,0x3f753f6d,0xbe953ec4,0x3f623ec4,0x3ef13f6d,0xbdc93f0e,0xbf7fbf55,0x3f223f7b,0xbf46be48,
0x3f353f80,0xbf350000,0x3f353f80,0xbf350000,0xbf350000,0xbf35bf80,0xbf350000,0xbf35bf80,0xbf35bf80,0x3f350000,0xbf35bf80,0x3f350000,
0x3f350000,0x3f353f80,0x3f350000,0x3f353f80,0xbf22bf80,0x3f460000,0x3dc9bf35,0x3f7f3f35,0x3f623e48,0x3ef13f7b,0x3f753f55,0xbe953f0e,
0x3e953f6d,0xbf75bec4,0xbef13ec4,0xbf62bf6d,0xbf7fbf0e,0xbdc9bf55,0xbf46bf7b,0x3f22be48,0x3f0e3f80,0xbf550000,0xbf550000,0xbf0ebf80,
0xbf7bbec4,0xbe48bf6d,0xbe48bf6d,0x3f7b3ec4,0x3e48bf35,0x3f7b3f35,0x3f7b3f35,0xbe483f35,0x3f553f6d,0xbf0e3ec4,0xbf0e3ec4,0xbf55bf6d,
0xbef1bf80,0x3f620000,0x3f753f35,0xbe953f35,0x3f7f3f0e,0xbdc93f55,0xbf463e48,0xbf22bf7b,0xbf223ec4,0xbf46bf6d,0xbdc9bf6d,0x3f7f3ec4,
0xbe95bf7b,0x3f753e48,0x3f623f55,0xbef13f0e,0x3ec43f80,0xbf6d0000,0xbec4bf80,0x3f6d0000,0xbf6dbf35,0x3ec4bf35,0x3f6d3f35,0xbec43f35,
0x3f6d0000,0x3ec43f80,0xbf6d0000,0xbec4bf80,0xbec43f35,0xbf6dbf35,0x3ec4bf35,0x3f6d3f35,0xbe95bf80,0x3f750000,0xbef13f35,0xbf62bf35,
0x3f463f55,0xbf223f0e,0xbdc9bf7b,0x3f7f3e48,0xbf7fbec4,0x3dc9bf6d,0x3f223f6d,0xbf463ec4,0x3f62be48,0x3ef13f7b,0xbf75bf0e,0x3e95bf55,
0x3e483f80,0xbf7b0000,0x3f7b0000,0x3e483f80,0xbf0ebf6d,0x3f55bec4,0xbf553ec4,0xbf0ebf6d,0x3f553f35,0xbf0e3f35,0x3f0ebf35,0x3f553f35,
0xbf7bbec4,0x3e48bf6d,0xbe483f6d,0xbf7bbec4,0xbdc9bf80,0x3f7f0000,0xbf46bf35,0x3f22bf35,0x3e953f7b,0xbf753e48,0x3f623f0e,0xbef13f55,
0xbef1bf6d,0x3f62bec4,0xbf75bec4,0x3e95bf6d,0x3f223f55,0xbf463f0e,0x3f7f3e48,0xbdc93f7b,0x3f80,0xbf800000,0x3f80,0xbf800000,
0xbf80,0x3f800000,0xbf80,0x3f800000,0x3f80,0xbf800000,0x3f80,0xbf800000,0xbf80,0x3f800000,0xbf80,0x3f800000,
0x3dc9bf80,0x3f7f0000,0x3f46bf35,0x3f223f35,0xbe953f7b,0xbf75be48,0xbf623f0e,0xbef1bf55,0x3ef1bf6d,0x3f623ec4,0x3f75bec4,0x3e953f6d,
0xbf223f55,0xbf46bf0e,0xbf7f3e48,0xbdc9bf7b,0xbe483f80,0xbf7b0000,0xbf7b0000,0x3e48bf80,0x3f0ebf6d,0x3f553ec4,0x3f553ec4,0xbf0e3f6d,
0xbf553f35,0xbf0ebf35,0xbf0ebf35,0x3f55bf35,0x3f7bbec4,0x3e483f6d,0x3e483f6d,0xbf7b3ec4,0x3e95bf80,0x3f750000,0x3ef13f35,0xbf623f35,
0xbf463f55,0xbf22bf0e,0x3dc9bf7b,0x3f7fbe48,0x3f7fbec4,0x3dc93f6d,0xbf223f6d,0xbf46bec4,0xbf62be48,0x3ef1bf7b,0x3f75bf0e,0x3e953f55,
0xbec43f80,0xbf6d0000,0x3ec4bf80,0x3f6d0000,0x3f6dbf35,0x3ec43f35,0xbf6d3f35,0xbec4bf35,0xbf6d0000,0x3ec4bf80,0x3f6d0000,0xbec43f80,
0x3ec43f35,0xbf6d3f35,0xbec4bf35,0x3f6dbf35,0x3ef1bf80,0x3f620000,0xbf753f35,0xbe95bf35,0xbf7f3f0e,0xbdc9bf55,0x3f463e48,0xbf223f7b,
0x3f223ec4,0xbf463f6d,0x3dc9bf6d,0x3f7fbec4,0x3e95bf7b,0x3f75be48,0xbf623f55,0xbef1bf0e,0xbf0e3f80,0xbf550000,0x3f550000,0xbf0e3f80,
0x3f7bbec4,0xbe483f6d,0x3e48bf6d,0x3f7bbec4,0xbe48bf35,0x3f7bbf35,0xbf7b3f35,0xbe48bf35,0xbf553f6d,0xbf0ebec4,0x3f0e3ec4,0xbf553f6d,
0x3f22bf80,0x3f460000,0xbdc9bf35,0x3f7fbf35,0xbf623e48,0x3ef1bf7b,0xbf753f55,0xbe95bf0e,0xbe953f6d,0xbf753ec4,0x3ef13ec4,0xbf623f6d,
0x3f7fbf0e,0xbdc93f55,0x3f46bf7b,0x3f223e48,0xbf353f80,0xbf350000,0xbf353f80,0xbf350000,0x3f350000,0xbf353f80,0x3f350000,0xbf353f80,
0x3f35bf80,0x3f350000,0x3f35bf80,0x3f350000,0xbf350000,0x3f35bf80,0xbf350000,0x3f35bf80,0x3f46bf80,0x3f220000,0x3f7fbf35,0xbdc93f35,
0xbef1be48,0x3f62bf7b,0x3e95bf55,0x3f75bf0e,0xbf753f6d,0xbe95bec4,0xbf623ec4,0x3ef1bf6d,0x3dc93f0e,0xbf7f3f55,0xbf223f7b,0xbf463e48,
0xbf553f80,0xbf0e0000,0xbf0e0000,0x3f55bf80,0x3e483ec4,0xbf7b3f6d,0xbf7b3f6d,0xbe48bec4,0x3f7bbf35,0xbe483f35,0xbe483f35,0xbf7b3f35,
0x3f0ebf6d,0x3f55bec4,0x3f55bec4,0xbf0e3f6d,0x3f62bf80,0x3ef10000,0xbe953f35,0xbf753f35,0x3dc9bf0e,0x3f7fbf55,0x3f22be48,0xbf463f7b,
0xbf463ec4,0x3f22bf6d,0x3f7fbf6d,0x3dc93ec4,0xbf753f7b,0xbe95be48,0x3ef1bf55,0x3f62bf0e,0xbf6d3f80,0xbec40000,0x3f6dbf80,0x3ec40000,
0xbec43f35,0xbf6d3f35,0x3ec4bf35,0x3f6dbf35,0x3ec40000,0xbf6d3f80,0xbec40000,0x3f6dbf80,0x3f6dbf35,0xbec43f35,0xbf6d3f35,0x3ec4bf35,
0x3f75bf80,0x3e950000,0xbf623f35,0x3ef1bf35,0x3f22bf55,0x3f46bf0e,0xbf7f3f7b,0xbdc9be48,0x3dc9bec4,0x3f7fbf6d,0xbf463f6d,0xbf223ec4,
0xbef13e48,0x3f62bf7b,0xbe953f0e,0xbf753f55,0xbf7b3f80,0xbe480000,0x3e480000,0xbf7b3f80,0xbf553f6d,0xbf0e3ec4,0x3f0ebec4,0xbf553f6d,
0xbf0e3f35,0xbf553f35,0x3f55bf35,0xbf0e3f35,0xbe483ec4,0xbf7b3f6d,0x3f7bbf6d,0xbe483ec4,0x3f7fbf80,0x3dc90000,0x3f22bf35,0x3f46bf35,
0x3f75bf7b,0x3e95be48,0x3ef1bf0e,0x3f62bf55,0x3f62bf6d,0x3ef1bec4,0x3e95bec4,0x3f75bf6d,0x3f46bf55,0x3f22bf0e,0x3dc9be48,0x3f7fbf7b,
0x3f803f80,0xbf803f80,0x3f803f80,0xbf803f80,0x3f803f80,0xbf803f80,0x3f803f80,0xbf803f80,0x3f803f80,0xbf803f80,0x3f803f80,0xbf803f80,
0x3f803f80,0xbf803f80,0x3f803f80,0xbf803f80,0x3dc90000,0x3f7f3f80,0x3f463f35,0x3f223f35,0x3e953e48,0x3f753f7b,0x3f623f55,0x3ef13f0e,
0x3ef13ec4,0x3f623f6d,0x3f753f6d,0x3e953ec4,0x3f223f0e,0x3f463f55,0x3f7f3f7b,0x3dc93e48,0xbf7bbf80,0x3e480000,0x3e480000,0x3f7b3f80,
0xbf55bf6d,0x3f0e3ec4,0x3f0e3ec4,0x3f553f6d,0xbf0ebf35,0x3f553f35,0x3f553f35,0x3f0e3f35,0xbe48bec4,0x3f7b3f6d,0x3f7b3f6d,0x3e483ec4,
0xbe950000,0xbf75bf80,0xbef1bf35,0x3f623f35,0xbf46bf0e,0xbf22bf55,0x3dc9be48,0x3f7f3f7b,0xbf7fbf6d,0xbdc9bec4,0x3f223ec4,0x3f463f6d,
0xbf62bf7b,0x3ef13e48,0x3f753f55,0x3e953f0e,0x3f6d3f80,0xbec40000,0xbf6dbf80,0x3ec40000,0x3ec43f35,0xbf6dbf35,0xbec4bf35,0x3f6d3f35,
0xbec40000,0xbf6dbf80,0x3ec40000,0x3f6d3f80,0xbf6dbf35,0xbec4bf35,0x3f6d3f35,0x3ec43f35,0x3ef10000,0x3f623f80,0xbf75bf35,0xbe95bf35,
0x3f7f3f55,0x3dc93f0e,0xbf46bf7b,0x3f223e48,0x3f223f6d,0xbf46bec4,0x3dc9bec4,0x3f7f3f6d,0xbe953e48,0xbf75bf7b,0x3f623f0e,0x3ef13f55,
0xbf55bf80,0x3f0e0000,0xbf0e0000,0xbf55bf80,0x3e48bec4,0x3f7b3f6d,0xbf7bbf6d,0x3e48bec4,0x3f7b3f35,0x3e483f35,0xbe48bf35,0x3f7b3f35,
0x3f0e3f6d,0xbf55bec4,0x3f553ec4,0x3f0e3f6d,0xbf220000,0xbf46bf80,0x3dc93f35,0xbf7fbf35,0xbf62bf7b,0x3ef1be48,0xbf75bf0e,0xbe95bf55,
0x3e95bec4,0x3f753f6d,0xbef1bf6d,0x3f623ec4,0x3f7f3f55,0xbdc93f0e,0x3f463e48,0x3f223f7b,0x3f353f80,0xbf350000,0x3f353f80,0xbf350000,
0xbf350000,0xbf35bf80,0xbf350000,0xbf35bf80,0xbf35bf80,0x3f350000,0xbf35bf80,0x3f350000,0x3f350000,0x3f353f80,0x3f350000,0x3f353f80,
0x3f460000,0x3f223f80,0x3f7f3f35,0xbdc93f35,0x3ef13f7b,0xbf62be48,0xbe953f0e,0xbf75bf55,0xbf75bec4,0xbe95bf6d,0xbf62bf6d,0x3ef1bec4,
0xbdc9bf55,0x3f7f3f0e,0x3f22be48,0x3f463f7b,0xbf0ebf80,0x3f550000,0x3f550000,0x3f0e3f80,0x3f7b3ec4,0x3e483f6d,0x3e483f6d,0xbf7bbec4,
0xbe483f35,0xbf7bbf35,0xbf7bbf35,0x3e48bf35,0xbf55bf6d,0x3f0ebec4,0x3f0ebec4,0x3f553f6d,0xbf620000,0xbef1bf80,0x3e95bf35,0x3f753f35,
0x3dc9bf55,0x3f7f3f0e,0x3f223f7b,0xbf463e48,0x3f463f6d,0xbf223ec4,0xbf7fbec4,0xbdc9bf6d,0xbf75be48,0xbe95bf7b,0x3ef1bf0e,0x3f623f55,
0x3ec43f80,0xbf6d0000,0xbec4bf80,0x3f6d0000,0xbf6dbf35,0x3ec4bf35,0x3f6d3f35,0xbec43f35,0x3f6d0000,0x3ec43f80,0xbf6d0000,0xbec4bf80,
0xbec43f35,0xbf6dbf35,0x3ec4bf35,0x3f6d3f35,0x3f750000,0x3e953f80,0xbf62bf35,0x3ef1bf35,0xbf223f0e,0xbf46bf55,0x3f7f3e48,0x3dc93f7b,
0x3dc9bf6d,0x3f7f3ec4,0xbf463ec4,0xbf22bf6d,0x3ef13f7b,0xbf623e48,0x3e95bf55,0x3f753f0e,0xbe48bf80,0x3f7b0000,0xbf7b0000,0xbe48bf80,
0x3f0e3f6d,0xbf553ec4,0x3f55bec4,0x3f0e3f6d,0xbf55bf35,0x3f0ebf35,0xbf0e3f35,0xbf55bf35,0x3f7b3ec4,0xbe483f6d,0x3e48bf6d,0x3f7b3ec4,
0xbf7f0000,0xbdc9bf80,0xbf223f35,0xbf46bf35,0x3f75be48,0x3e953f7b,0x3ef1bf55,0x3f623f0e,0xbf623ec4,0xbef1bf6d,0xbe953f6d,0xbf75bec4,
0x3f46bf0e,0x3f223f55,0x3dc9bf7b,0x3f7f3e48,0x3f80,0xbf800000,0x3f80,0xbf800000,0xbf80,0x3f800000,0xbf80,0x3f800000,
0x3f80,0xbf800000,0x3f80,0xbf800000,0xbf80,0x3f800000,0xbf80,0x3f800000,0x3f7f0000,0xbdc93f80,0x3f223f35,0xbf463f35,
0xbf75be48,0x3e95bf7b,0xbef1bf55,0x3f62bf0e,0x3f623ec4,0xbef13f6d,0x3e953f6d,0xbf753ec4,0xbf46bf0e,0x3f22bf55,0xbdc9bf7b,0x3f7fbe48,
0x3e48bf80,0x3f7b0000,0x3f7b0000,0xbe483f80,0xbf0e3f6d,0xbf55bec4,0xbf55bec4,0x3f0ebf6d,0x3f55bf35,0x3f0e3f35,0x3f0e3f35,0xbf553f35,
0xbf7b3ec4,0xbe48bf6d,0xbe48bf6d,0x3f7bbec4,0xbf750000,0x3e95bf80,0x3f62bf35,0x3ef13f35,0x3f223f0e,0xbf463f55,0xbf7f3e48,0x3dc9bf7b,
0xbdc9bf6d,0x3f7fbec4,0x3f463ec4,0xbf223f6d,0xbef13f7b,0xbf62be48,0xbe95bf55,0x3f75bf0e,0xbec43f80,0xbf6d0000,0x3ec4bf80,0x3f6d0000,
0x3f6dbf35,0x3ec43f35,0xbf6d3f35,0xbec4bf35,0xbf6d0000,0x3ec4bf80,0x3f6d0000,0xbec43f80,0x3ec43f35,0xbf6d3f35,0xbec4bf35,0x3f6dbf35,
0x3f620000,0xbef13f80,0xbe95bf35,0x3f75bf35,0xbdc9bf55,0x3f7fbf0e,0xbf223f7b,0xbf46be48,0xbf463f6d,0xbf22bec4,0x3f7fbec4,0xbdc93f6d,
0x3f75be48,0xbe953f7b,0xbef1bf0e,0x3f62bf55,0x3f0ebf80,0x3f550000,0xbf550000,0x3f0ebf80,0xbf7b3ec4,0x3e48bf6d,0xbe483f6d,0xbf7b3ec4,
0x3e483f35,0xbf7b3f35,0x3f7bbf35,0x3e483f35,0x3f55bf6d,0x3f0e3ec4,0xbf0ebec4,0x3f55bf6d,0xbf460000,0x3f22bf80,0xbf7f3f35,0xbdc9bf35,
0xbef13f7b,0xbf623e48,0x3e953f0e,0xbf753f55,0x3f75bec4,0xbe953f6d,0x3f62bf6d,0x3ef13ec4,0x3dc9bf55,0x3f7fbf0e,0xbf22be48,0x3f46bf7b,
0xbf353f80,0xbf350000,0xbf353f80,0xbf350000,0x3f350000,0xbf353f80,0x3f350000,0xbf353f80,0x3f35bf80,0x3f350000,0x3f35bf80,0x3f350000,
0xbf350000,0x3f35bf80,0xbf350000,0x3f35bf80,0x3f220000,0xbf463f80,0xbdc93f35,0xbf7f3f35,0x3f62bf7b,0x3ef13e48,0x3f75bf0e,0xbe953f55,
0xbe95bec4,0x3f75bf6d,0x3ef1bf6d,0x3f62bec4,0xbf7f3f55,0xbdc9bf0e,0xbf463e48,0x3f22bf7b,0x3f55bf80,0x3f0e0000,0x3f0e0000,0xbf553f80,
0xbe48bec4,0x3f7bbf6d,0x3f7bbf6d,0x3e483ec4,0xbf7b3f35,0x3e48bf35,0x3e48bf35,0x3f7bbf35,0xbf0e3f6d,0xbf553ec4,0xbf553ec4,0x3f0ebf6d,
0xbef10000,0x3f62bf80,0x3f75bf35,0xbe953f35,0xbf7f3f55,0x3dc9bf0e,0x3f46bf7b,0x3f22be48,0xbf223f6d,0xbf463ec4,0xbdc9bec4,0x3f7fbf6d,
0x3e953e48,0xbf753f7b,0xbf623f0e,0x3ef1bf55,0xbf6d3f80,0xbec40000,0x3f6dbf80,0x3ec40000,0xbec43f35,0xbf6d3f35,0x3ec4bf35,0x3f6dbf35,
0x3ec40000,0xbf6d3f80,0xbec40000,0x3f6dbf80,0x3f6dbf35,0xbec43f35,0xbf6d3f35,0x3ec4bf35,0x3e950000,0xbf753f80,0x3ef1bf35,0x3f62bf35,
0x3f46bf0e,0xbf223f55,0xbdc9be48,0x3f7fbf7b,0x3f7fbf6d,0xbdc93ec4,0xbf223ec4,0x3f46bf6d,0x3f62bf7b,0x3ef1be48,0xbf753f55,0x3e95bf0e,
0x3f7bbf80,0x3e480000,0xbe480000,0x3f7bbf80,0x3f55bf6d,0x3f0ebec4,0xbf0e3ec4,0x3f55bf6d,0x3f0ebf35,0x3f55bf35,0xbf553f35,0x3f0ebf35,
0x3e48bec4,0x3f7bbf6d,0xbf7b3f6d,0x3e48bec4,0xbdc90000,0x3f7fbf80,0xbf463f35,0x3f22bf35,0xbe953e48,0x3f75bf7b,0xbf623f55,0x3ef1bf0e,
0xbef13ec4,0x3f62bf6d,0xbf753f6d,0x3e95bec4,0xbf223f0e,0x3f46bf55,0xbf7f3f7b,0x3dc9be48,0x40003f80,0x3fb53f80,0x3f80,0xbfb53f80,
0x40004000,0xbfb50000,0x0,0xbfb5c000,0x40004000,0xbfb5c000,0x0,0x3fb50000,0x40004000,0x3fb50000,0x0,0x3fb54000,
0x3fff3f80,0x3fa23f80,0xbe49bf80,0xbfc6bf80,0x3ff53ffb,0xbfe2bec8,0xbf15bec8,0xbf71bffb,0x3fe23fed,0xbf15bfed,0xbf71bf44,0x3ff53f44,
0x3fc63fd5,0x3fff3f8e,0xbfa2bf8e,0x3e493fd5,0x3ffb3f80,0x3f8e3f80,0xbec83f80,0xbfd53f80,0x3fd53fed,0xbffbbf44,0xbf8ebf44,0xbec8bfed,
0x3f8e3fb5,0x3ec8bfb5,0xbfd5bfb5,0x3ffb3fb5,0x3ec83f44,0x3fd53fed,0xbffbbfed,0xbf8e3f44,0x3ff53f80,0x3f713f80,0xbf15bf80,0xbfe2bf80,
0x3fa23fd5,0xbfffbf8e,0xbfc6bf8e,0x3e49bfd5,0x3e493f44,0x3fa2bf44,0xbfffbfed,0x3fc63fed,0xbf71bec8,0x3f153ffb,0xbfe2bffb,0xbff5bec8,
0x3fed3f80,0x3f443f80,0xbf443f80,0xbfed3f80,0x3f443fb5,0xbfedbfb5,0xbfedbfb5,0x3f44bfb5,0xbf440000,0x3fed0000,0xbfedc000,0x3f444000,
0xbfedbfb5,0xbf443fb5,0xbf44bfb5,0xbfedbfb5,0x3fe23f80,0x3f153f80,0xbf71bf80,0xbff5bf80,0x3e493f8e,0xbfc6bfd5,0xbfffbfd5,0x3fa2bf8e,
0xbfc6bf44,0x3fff3f44,0xbfa2bfed,0xbe493fed,0xbff5bffb,0xbfe23ec8,0x3f15bec8,0xbf71bffb,0x3fd53f80,0x3ec83f80,0xbf8e3f80,0xbffb3f80,
0xbec83f44,0xbf8ebfed,0xbffbbfed,0x3fd5bf44,0xbffbbfb5,0x3fd53fb5,0xbec8bfb5,0xbf8e3fb5,0xbf8ebfed,0xbffbbf44,0x3fd53f44,0x3ec8bfed,
0x3fc63f80,0x3e493f80,0xbfa2bf80,0xbfffbf80,0xbf713ec8,0xbf15bffb,0xbfe2bffb,0x3ff5bec8,0xbff5bfed,0x3f713fed,0x3f15bf44,0xbfe23f44,
0x3e49bf8e,0xbfa2bfd5,0x3fff3fd5,0x3fc6bf8e,0x3f80,0xbfb53f80,0xc0003f80,0xbfb53f80,0xc000,0x3fb50000,0x40000000,0xbfb54000,
0x4000,0x3fb5c000,0xc0000000,0x3fb50000,0xc000,0xbfb50000,0x40000000,0x3fb5c000,0xbe493f80,0xbfc63f80,0xbfffbf80,0xbfa2bf80,
0x3f15bffb,0x3f713ec8,0x3ff53ec8,0xbfe23ffb,0xbf713fed,0x3ff5bfed,0xbfe2bf44,0x3f153f44,0x3fa2bfd5,0xbe49bf8e,0x3fc63f8e,0x3fffbfd5,
0xbec83f80,0xbfd53f80,0xbffb3f80,0xbf8e3f80,0x3f8ebfed,0x3ec83f44,0x3fd53f44,0xbffb3fed,0xbfd53fb5,0x3ffbbfb5,0xbf8ebfb5,0xbec83fb5,
0x3ffbbf44,0x3f8ebfed,0x3ec83fed,0x3fd5bf44,0xbf153f80,0xbfe23f80,0xbff5bf80,0xbf71bf80,0x3fc6bfd5,0xbe493f8e,0x3fa23f8e,0xbfff3fd5,
0xbfff3f44,0x3fc6bf44,0xbe49bfed,0xbfa23fed,0x3fe23ec8,0x3ff5bffb,0xbf713ffb,0x3f153ec8,0xbf443f80,0xbfed3f80,0xbfed3f80,0xbf443f80,
0x3fedbfb5,0xbf443fb5,0x3f443fb5,0xbfed3fb5,0xbfed0000,0x3f440000,0x3f44c000,0xbfed4000,0x3f443fb5,0x3fedbfb5,0xbfed3fb5,0xbf443fb5,
0xbf713f80,0xbff53f80,0xbfe2bf80,0xbf15bf80,0x3fffbf8e,0xbfa23fd5,0x3e493fd5,0xbfc63f8e,0xbfa2bf44,0xbe493f44,0x3fc6bfed,0xbfff3fed,
0xbf153ffb,0x3f71bec8,0xbff53ec8,0xbfe23ffb,0xbf8e3f80,0xbffb3f80,0xbfd53f80,0xbec83f80,0x3ffbbf44,0xbfd53fed,0xbec83fed,0xbf8e3f44,
0xbec8bfb5,0xbf8e3fb5,0x3ffbbfb5,0xbfd53fb5,0xbfd53fed,0xbec83f44,0xbf8ebf44,0xbffb3fed,0xbfa23f80,0xbfff3f80,0xbfc6bf80,0xbe49bf80,
0x3fe2bec8,0xbff53ffb,0xbf713ffb,0xbf153ec8,0x3f15bfed,0xbfe23fed,0x3ff5bf44,0xbf713f44,0xbfff3f8e,0xbfc63fd5,0x3e49bfd5,0xbfa23f8e,
0xc0003f80,0xbfb53f80,0x3f80,0x3fb53f80,0xc0004000,0x3fb50000,0x0,0x3fb5c000,0xc0004000,0x3fb5c000,0x0,0xbfb50000,
0xc0004000,0xbfb50000,0x0,0xbfb54000,0xbfff3f80,0xbfa23f80,0x3e49bf80,0x3fc6bf80,0xbff53ffb,0x3fe2bec8,0x3f15bec8,0x3f71bffb,
0xbfe23fed,0x3f15bfed,0x3f71bf44,0xbff53f44,0xbfc63fd5,0xbfff3f8e,0x3fa2bf8e,0xbe493fd5,0xbffb3f80,0xbf8e3f80,0x3ec83f80,0x3fd53f80,
0xbfd53fed,0x3ffbbf44,0x3f8ebf44,0x3ec8bfed,0xbf8e3fb5,0xbec8bfb5,0x3fd5bfb5,0xbffb3fb5,0xbec83f44,0xbfd53fed,0x3ffbbfed,0x3f8e3f44,
0xbff53f80,0xbf713f80,0x3f15bf80,0x3fe2bf80,0xbfa23fd5,0x3fffbf8e,0x3fc6bf8e,0xbe49bfd5,0xbe493f44,0xbfa2bf44,0x3fffbfed,0xbfc63fed,
0x3f71bec8,0xbf153ffb,0x3fe2bffb,0x3ff5bec8,0xbfed3f80,0xbf443f80,0x3f443f80,0x3fed3f80,0xbf443fb5,0x3fedbfb5,0x3fedbfb5,0xbf44bfb5,
0x3f440000,0xbfed0000,0x3fedc000,0xbf444000,0x3fedbfb5,0x3f443fb5,0x3f44bfb5,0x3fedbfb5,0xbfe23f80,0xbf153f80,0x3f71bf80,0x3ff5bf80,
0xbe493f8e,0x3fc6bfd5,0x3fffbfd5,0xbfa2bf8e,0x3fc6bf44,0xbfff3f44,0x3fa2bfed,0x3e493fed,0x3ff5bffb,0x3fe23ec8,0xbf15bec8,0x3f71bffb,
0xbfd53f80,0xbec83f80,0x3f8e3f80,0x3ffb3f80,0x3ec83f44,0x3f8ebfed,0x3ffbbfed,0xbfd5bf44,0x3ffbbfb5,0xbfd53fb5,0x3ec8bfb5,0x3f8e3fb5,
0x3f8ebfed,0x3ffbbf44,0xbfd53f44,0xbec8bfed,0xbfc63f80,0xbe493f80,0x3fa2bf80,0x3fffbf80,0x3f713ec8,0x3f15bffb,0x3fe2bffb,0xbff5bec8,
0x3ff5bfed,0xbf713fed,0xbf15bf44,0x3fe23f44,0xbe49bf8e,0x3fa2bfd5,0xbfff3fd5,0xbfc6bf8e,0x3f80,0x3fb53f80,0x40003f80,0x3fb53f80,
0xc000,0xbfb50000,0xc0000000,0x3fb54000,0x4000,0xbfb5c000,0x40000000,0xbfb50000,0xc000,0x3fb50000,0xc0000000,0xbfb5c000,
0x3e493f80,0x3fc63f80,0x3fffbf80,0x3fa2bf80,0xbf15bffb,0xbf713ec8,0xbff53ec8,0x3fe23ffb,0x3f713fed,0xbff5bfed,0x3fe2bf44,0xbf153f44,
0xbfa2bfd5,0x3e49bf8e,0xbfc63f8e,0xbfffbfd5,0x3ec83f80,0x3fd53f80,0x3ffb3f80,0x3f8e3f80,0xbf8ebfed,0xbec83f44,0xbfd53f44,0x3ffb3fed,
0x3fd53fb5,0xbffbbfb5,0x3f8ebfb5,0x3ec83fb5,0xbffbbf44,0xbf8ebfed,0xbec83fed,0xbfd5bf44,0x3f153f80,0x3fe23f80,0x3ff5bf80,0x3f71bf80,
0xbfc6bfd5,0x3e493f8e,0xbfa23f8e,0x3fff3fd5,0x3fff3f44,0xbfc6bf44,0x3e49bfed,0x3fa23fed,0xbfe23ec8,0xbff5bffb,0x3f713ffb,0xbf153ec8,
0x3f443f80,0x3fed3f80,0x3fed3f80,0x3f443f80,0xbfedbfb5,0x3f443fb5,0xbf443fb5,0x3fed3fb5,0x3fed0000,0xbf440000,0xbf44c000,0x3fed4000,
0xbf443fb5,0xbfedbfb5,0x3fed3fb5,0x3f443fb5,0x3f713f80,0x3ff53f80,0x3fe2bf80,0x3f15bf80,0xbfffbf8e,0x3fa23fd5,0xbe493fd5,0x3fc63f8e,
0x3fa2bf44,0x3e493f44,0xbfc6bfed,0x3fff3fed,0x3f153ffb,0xbf71bec8,0x3ff53ec8,0x3fe23ffb,0x3f8e3f80,0x3ffb3f80,0x3fd53f80,0x3ec83f80,
0xbffbbf44,0x3fd53fed,0x3ec83fed,0x3f8e3f44,0x3ec8bfb5,0x3f8e3fb5,0xbffbbfb5,0x3fd53fb5,0x3fd53fed,0x3ec83f44,0x3f8ebf44,0x3ffb3fed,
0x3fa23f80,0x3fff3f80,0x3fc6bf80,0x3e49bf80,0xbfe2bec8,0x3ff53ffb,0x3f713ffb,0x3f153ec8,0xbf15bfed,0x3fe23fed,0xbff5bf44,0x3f713f44,
0x3fff3f8e,0x3fc63fd5,0xbe49bfd5,0x3fa23f8e,0x40004000,0x3fb54000,0x0,0xbfb50000,0x40004000,0xbfb50000,0x0,0xbfb5c000,
0x40004000,0xbfb5c000,0x0,0x3fb50000,0x40004000,0x3fb50000,0x0,0x3fb54000,0x3fa23fb5,0xbe493fb5,0xbfc6bfb5,0xbfffbfb5,
0x3f713f8e,0xbff5bfd5,0xbfe2bfd5,0x3f15bf8e,0x3f153f44,0x3f71bf44,0xbff5bfed,0x3fe23fed,0x3e493ec8,0x3fc63ffb,0xbfffbffb,0xbfa23ec8,
0xbec80000,0xbfd50000,0xbffbc000,0xbf8ec000,0xbf8ebf44,0xbec8bfed,0xbfd5bfed,0x3ffb3f44,0xbfd5bfb5,0x3ffb3fb5,0xbf8ebfb5,0xbec83fb5,
0xbffbbfed,0xbf8e3f44,0xbec8bf44,0xbfd5bfed,0xbfe2bfb5,0xbff5bfb5,0xbf71bfb5,0x3f15bfb5,0xbfffbffb,0x3fc6bec8,0x3e49bec8,0x3fa23ffb,
0xbfc6bfed,0x3e493fed,0x3fa23f44,0xbfffbf44,0xbf15bf8e,0xbfe2bfd5,0x3ff53fd5,0x3f71bf8e,0xbfedc000,0xbf44c000,0x3f440000,0x3fed0000,
0xbf44bfb5,0x3fed3fb5,0x3fed3fb5,0xbf443fb5,0x3f440000,0xbfed0000,0x3fed4000,0xbf44c000,0x3fed3fb5,0x3f44bfb5,0x3f443fb5,0x3fed3fb5,
0xbf15bfb5,0x3f71bfb5,0x3ff53fb5,0x3fe23fb5,0x3fa23ec8,0x3e493ffb,0x3fc63ffb,0xbfffbec8,0x3fff3fed,0xbfa2bfed,0xbe493f44,0x3fc6bf44,
0x3f713fd5,0x3ff53f8e,0xbfe2bf8e,0xbf153fd5,0x3f8e0000,0x3ffb0000,0x3fd54000,0x3ec84000,0x3ffb3fed,0xbfd53f44,0xbec83f44,0xbf8ebfed,
0x3ec83fb5,0x3f8ebfb5,0xbffbbfb5,0x3fd53fb5,0xbfd5bf44,0xbec83fed,0xbf8ebfed,0xbffbbf44,0x3fff3fb5,0x3fc63fb5,0x3e493fb5,0xbfa23fb5,
0x3f153fd5,0xbfe2bf8e,0xbff5bf8e,0x3f71bfd5,0xbfe2bf44,0x3ff53f44,0xbf71bfed,0xbf153fed,0xbfa2bffb,0xbfffbec8,0x3fc63ec8,0x3e49bffb,
0x4000,0xbfb54000,0xc0000000,0xbfb50000,0xc000,0x3fb50000,0x40000000,0xbfb54000,0x4000,0x3fb5c000,0xc0000000,0x3fb50000,
0xc000,0xbfb50000,0x40000000,0x3fb5c000,0xbfc63fb5,0xbfff3fb5,0xbfa2bfb5,0x3e49bfb5,0x3fe2bf8e,0xbf153fd5,0x3f713fd5,0xbff53f8e,
0xbff53f44,0x3fe2bf44,0xbf15bfed,0xbf713fed,0x3fffbec8,0x3fa2bffb,0x3e493ffb,0x3fc6bec8,0xbffb0000,0xbf8e0000,0x3ec8c000,0x3fd5c000,
0x3fd53f44,0xbffb3fed,0xbf8e3fed,0xbec8bf44,0xbf8ebfb5,0xbec83fb5,0x3fd5bfb5,0xbffb3fb5,0x3ec83fed,0x3fd5bf44,0xbffb3f44,0xbf8e3fed,
0xbf71bfb5,0x3f15bfb5,0x3fe2bfb5,0x3ff5bfb5,0xbe493ffb,0xbfa23ec8,0xbfff3ec8,0x3fc6bffb,0x3fa2bfed,0xbfff3fed,0x3fc63f44,0xbe49bf44,
0xbff53f8e,0xbf713fd5,0xbf15bfd5,0xbfe23f8e,0x3f44c000,0x3fedc000,0x3fed0000,0x3f440000,0xbfed3fb5,0x3f44bfb5,0xbf44bfb5,0x3fedbfb5,
0x3fed0000,0xbf440000,0xbf444000,0x3fedc000,0xbf44bfb5,0xbfed3fb5,0x3fedbfb5,0x3f44bfb5,0x3ff5bfb5,0x3fe2bfb5,0x3f153fb5,0xbf713fb5,
0xbfc6bec8,0x3fffbffb,0x3fa2bffb,0x3e493ec8,0xbe493fed,0x3fc6bfed,0xbfff3f44,0x3fa2bf44,0x3fe2bfd5,0x3f15bf8e,0x3f713f8e,0x3ff5bfd5,
0x3fd50000,0x3ec80000,0xbf8e4000,0xbffb4000,0x3ec8bfed,0x3f8ebf44,0x3ffbbf44,0xbfd53fed,0xbffb3fb5,0x3fd5bfb5,0xbec8bfb5,0xbf8e3fb5,
0x3f8e3f44,0x3ffbbfed,0xbfd53fed,0xbec83f44,0x3e493fb5,0xbfa23fb5,0xbfff3fb5,0xbfc63fb5,0x3ff5bfd5,0xbf713f8e,0x3f153f8e,0xbfe23fd5,
0xbf71bf44,0xbf153f44,0x3fe2bfed,0xbff53fed,0xbfc63ffb,0xbe493ec8,0xbfa2bec8,0xbfff3ffb,0xc0004000,0xbfb54000,0x0,0x3fb50000,
0xc0004000,0x3fb50000,0x0,0x3fb5c000,0xc0004000,0x3fb5c000,0x0,0xbfb50000,0xc0004000,0xbfb50000,0x0,0xbfb54000,
0xbfa23fb5,0x3e493fb5,0x3fc6bfb5,0x3fffbfb5,0xbf713f8e,0x3ff5bfd5,0x3fe2bfd5,0xbf15bf8e,0xbf153f44,0xbf71bf44,0x3ff5bfed,0xbfe23fed,
0xbe493ec8,0xbfc63ffb,0x3fffbffb,0x3fa23ec8,0x3ec80000,0x3fd50000,0x3ffbc000,0x3f8ec000,0x3f8ebf44,0x3ec8bfed,0x3fd5bfed,0xbffb3f44,
0x3fd5bfb5,0xbffb3fb5,0x3f8ebfb5,0x3ec83fb5,0x3ffbbfed,0x3f8e3f44,0x3ec8bf44,0x3fd5bfed,0x3fe2bfb5,0x3ff5bfb5,0x3f71bfb5,0xbf15bfb5,
0x3fffbffb,0xbfc6bec8,0xbe49bec8,0xbfa23ffb,0x3fc6bfed,0xbe493fed,0xbfa23f44,0x3fffbf44,0x3f15bf8e,0x3fe2bfd5,0xbff53fd5,0xbf71bf8e,
0x3fedc000,0x3f44c000,0xbf440000,0xbfed0000,0x3f44bfb5,0xbfed3fb5,0xbfed3fb5,0x3f443fb5,0xbf440000,0x3fed0000,0xbfed4000,0x3f44c000,
0xbfed3fb5,0xbf44bfb5,0xbf443fb5,0xbfed3fb5,0x3f15bfb5,0xbf71bfb5,0xbff53fb5,0xbfe23fb5,0xbfa23ec8,0xbe493ffb,0xbfc63ffb,0x3fffbec8,
0xbfff3fed,0x3fa2bfed,0x3e493f44,0xbfc6bf44,0xbf713fd5,0xbff53f8e,0x3fe2bf8e,0x3f153fd5,0xbf8e0000,0xbffb0000,0xbfd54000,0xbec84000,
0xbffb3fed,0x3fd53f44,0x3ec83f44,0x3f8ebfed,0xbec83fb5,0xbf8ebfb5,0x3ffbbfb5,0xbfd53fb5,0x3fd5bf44,0x3ec83fed,0x3f8ebfed,0x3ffbbf44,
0xbfff3fb5,0xbfc63fb5,0xbe493fb5,0x3fa23fb5,0xbf153fd5,0x3fe2bf8e,0x3ff5bf8e,0xbf71bfd5,0x3fe2bf44,0xbff53f44,0x3f71bfed,0x3f153fed,
0x3fa2bffb,0x3fffbec8,0xbfc63ec8,0xbe49bffb,0x4000,0x3fb54000,0x40000000,0x3fb50000,0xc000,0xbfb50000,0xc0000000,0x3fb54000,
0x4000,0xbfb5c000,0x40000000,0xbfb50000,0xc000,0x3fb50000,0xc0000000,0xbfb5c000,0x3fc63fb5,0x3fff3fb5,0x3fa2bfb5,0xbe49bfb5,
0xbfe2bf8e,0x3f153fd5,0xbf713fd5,0x3ff53f8e,0x3ff53f44,0xbfe2bf44,0x3f15bfed,0x3f713fed,0xbfffbec8,0xbfa2bffb,0xbe493ffb,0xbfc6bec8,
0x3ffb0000,0x3f8e0000,0xbec8c000,0xbfd5c000,0xbfd53f44,0x3ffb3fed,0x3f8e3fed,0x3ec8bf44,0x3f8ebfb5,0x3ec83fb5,0xbfd5bfb5,0x3ffb3fb5,
0xbec83fed,0xbfd5bf44,0x3ffb3f44,0x3f8e3fed,0x3f71bfb5,0xbf15bfb5,0xbfe2bfb5,0xbff5bfb5,0x3e493ffb,0x3fa23ec8,0x3fff3ec8,0xbfc6bffb,
0xbfa2bfed,0x3fff3fed,0xbfc63f44,0x3e49bf44,0x3ff53f8e,0x3f713fd5,0x3f15bfd5,0x3fe23f8e,0xbf44c000,0xbfedc000,0xbfed0000,0xbf440000,
0x3fed3fb5,0xbf44bfb5,0x3f44bfb5,0xbfedbfb5,0xbfed0000,0x3f440000,0x3f444000,0xbfedc000,0x3f44bfb5,0x3fed3fb5,0xbfedbfb5,0xbf44bfb5,
0xbff5bfb5,0xbfe2bfb5,0xbf153fb5,0x3f713fb5,0x3fc6bec8,0xbfffbffb,0xbfa2bffb,0xbe493ec8,0x3e493fed,0xbfc6bfed,0x3fff3f44,0xbfa2bf44,
0xbfe2bfd5,0xbf15bf8e,0xbf713f8e,0xbff5bfd5,0xbfd50000,0xbec80000,0x3f8e4000,0x3ffb4000,0xbec8bfed,0xbf8ebf44,0xbffbbf44,0x3fd53fed,
0x3ffb3fb5,0xbfd5bfb5,0x3ec8bfb5,0x3f8e3fb5,0xbf8e3f44,0xbffbbfed,0x3fd53fed,0x3ec83f44,0xbe493fb5,0x3fa23fb5,0x3fff3fb5,0x3fc63fb5,
0xbff5bfd5,0x3f713f8e,0xbf153f8e,0x3fe23fd5,0x3f71bf44,0x3f153f44,0xbfe2bfed,0x3ff53fed,0x3fc63ffb,0x3e493ec8,0x3fa2bec8,0x3fff3ffb,
0x40004000,0x3fb54000,0x0,0xbfb50000,0x40004000,0xbfb50000,0x0,0xbfb5c000,0x40004000,0xbfb5c000,0x0,0x3fb50000,
0x40004000,0x3fb50000,0x0,0x3fb54000,0xbe490000,0xbfc60000,0xbfffc000,0xbfa2c000,0xbf15bec8,0xbf71bffb,0xbff5bffb,0x3fe23ec8,
0xbf71bf44,0x3ff53f44,0xbfe2bfed,0x3f153fed,0xbfa2bf8e,0x3e493fd5,0xbfc6bfd5,0xbfffbf8e,0xbffbc000,0xbf8ec000,0x3ec80000,0x3fd50000,
0xbfd5bfed,0x3ffb3f44,0x3f8e3f44,0x3ec83fed,0xbf8ebfb5,0xbec83fb5,0x3fd53fb5,0xbffbbfb5,0xbec8bf44,0xbfd5bfed,0x3ffb3fed,0x3f8ebf44,
0x3f150000,0x3fe20000,0x3ff54000,0x3f714000,0x3fc63f8e,0xbe493fd5,0x3fa23fd5,0xbfffbf8e,0x3fff3fed,0xbfc6bfed,0x3e493f44,0x3fa2bf44,
0x3fe23ffb,0x3ff53ec8,0xbf71bec8,0x3f153ffb,0x3fed4000,0x3f444000,0xbf440000,0xbfed0000,0x3f443fb5,0xbfedbfb5,0xbfedbfb5,0x3f44bfb5,
0xbf440000,0x3fed0000,0xbfedc000,0x3f444000,0xbfedbfb5,0xbf443fb5,0xbf44bfb5,0xbfedbfb5,0xbf710000,0xbff50000,0xbfe2c000,0xbf15c000,
0xbfffbfd5,0x3fa2bf8e,0xbe49bf8e,0x3fc63fd5,0xbfa2bfed,0xbe493fed,0x3fc63f44,0xbfffbf44,0x3f15bec8,0xbf71bffb,0x3ff53ffb,0x3fe2bec8,
0xbfd5c000,0xbec8c000,0x3f8e0000,0x3ffb0000,0x3ec8bf44,0x3f8e3fed,0x3ffb3fed,0xbfd53f44,0x3ffb3fb5,0xbfd5bfb5,0x3ec83fb5,0x3f8ebfb5,
0x3f8e3fed,0x3ffb3f44,0xbfd5bf44,0xbec83fed,0x3fa20000,0x3fff0000,0x3fc64000,0x3e494000,0x3fe23ffb,0xbff53ec8,0xbf713ec8,0xbf15bffb,
0xbf153f44,0x3fe2bf44,0xbff5bfed,0x3f713fed,0xbfffbfd5,0xbfc63f8e,0x3e49bf8e,0xbfa2bfd5,0x4000,0xbfb54000,0xc0000000,0xbfb50000,
0xc000,0x3fb50000,0x40000000,0xbfb54000,0x4000,0x3fb5c000,0xc0000000,0x3fb50000,0xc000,0xbfb50000,0x40000000,0x3fb5c000,
0xbfff0000,0xbfa20000,0x3e49c000,0x3fc6c000,0x3ff53ec8,0xbfe23ffb,0xbf153ffb,0xbf71bec8,0xbfe2bf44,0x3f153f44,0x3f71bfed,0xbff53fed,
0x3fc63f8e,0x3fffbfd5,0xbfa23fd5,0x3e493f8e,0x3ec8c000,0x3fd5c000,0x3ffb0000,0x3f8e0000,0xbf8e3fed,0xbec8bf44,0xbfd5bf44,0x3ffbbfed,
0x3fd5bfb5,0xbffb3fb5,0x3f8e3fb5,0x3ec8bfb5,0xbffb3f44,0xbf8e3fed,0xbec8bfed,0xbfd53f44,0x3ff50000,0x3f710000,0xbf154000,0xbfe24000,
0xbfa2bf8e,0x3fffbfd5,0x3fc6bfd5,0xbe493f8e,0x3e493fed,0x3fa2bfed,0xbfff3f44,0x3fc6bf44,0x3f71bffb,0xbf15bec8,0x3fe23ec8,0x3ff5bffb,
0xbf444000,0xbfed4000,0xbfed0000,0xbf440000,0x3fedbfb5,0xbf443fb5,0x3f443fb5,0xbfed3fb5,0xbfed0000,0x3f440000,0x3f44c000,0xbfed4000,
0x3f443fb5,0x3fedbfb5,0xbfed3fb5,0xbf443fb5,0xbfe20000,0xbf150000,0x3f71c000,0x3ff5c000,0x3e493fd5,0xbfc63f8e,0xbfff3f8e,0x3fa2bfd5,
0x3fc6bfed,0xbfff3fed,0x3fa23f44,0x3e49bf44,0xbff53ec8,0xbfe23ffb,0x3f15bffb,0xbf713ec8,0x3f8ec000,0x3ffbc000,0x3fd50000,0x3ec80000,
0xbffb3f44,0x3fd5bfed,0x3ec8bfed,0x3f8ebf44,0x3ec83fb5,0x3f8ebfb5,0xbffb3fb5,0x3fd5bfb5,0x3fd5bfed,0x3ec8bf44,0x3f8e3f44,0x3ffbbfed,
0x3fc60000,0x3e490000,0xbfa24000,0xbfff4000,0x3f71bffb,0x3f15bec8,0x3fe2bec8,0xbff53ffb,0xbff53f44,0x3f71bf44,0x3f15bfed,0xbfe23fed,
0xbe493fd5,0x3fa2bf8e,0xbfff3f8e,0xbfc63fd5,0xc0004000,0xbfb54000,0x0,0x3fb50000,0xc0004000,0x3fb50000,0x0,0x3fb5c000,
0xc0004000,0x3fb5c000,0x0,0xbfb50000,0xc0004000,0xbfb50000,0x0,0xbfb54000,0x3e490000,0x3fc60000,0x3fffc000,0x3fa2c000,
0x3f15bec8,0x3f71bffb,0x3ff5bffb,0xbfe23ec8,0x3f71bf44,0xbff53f44,0x3fe2bfed,0xbf153fed,0x3fa2bf8e,0xbe493fd5,0x3fc6bfd5,0x3fffbf8e,
0x3ffbc000,0x3f8ec000,0xbec80000,0xbfd50000,0x3fd5bfed,0xbffb3f44,0xbf8e3f44,0xbec83fed,0x3f8ebfb5,0x3ec83fb5,0xbfd53fb5,0x3ffbbfb5,
0x3ec8bf44,0x3fd5bfed,0xbffb3fed,0xbf8ebf44,0xbf150000,0xbfe20000,0xbff54000,0xbf714000,0xbfc63f8e,0x3e493fd5,0xbfa23fd5,0x3fffbf8e,
0xbfff3fed,0x3fc6bfed,0xbe493f44,0xbfa2bf44,0xbfe23ffb,0xbff53ec8,0x3f71bec8,0xbf153ffb,0xbfed4000,0xbf444000,0x3f440000,0x3fed0000,
0xbf443fb5,0x3fedbfb5,0x3fedbfb5,0xbf44bfb5,0x3f440000,0xbfed0000,0x3fedc000,0xbf444000,0x3fedbfb5,0x3f443fb5,0x3f44bfb5,0x3fedbfb5,
0x3f710000,0x3ff50000,0x3fe2c000,0x3f15c000,0x3fffbfd5,0xbfa2bf8e,0x3e49bf8e,0xbfc63fd5,0x3fa2bfed,0x3e493fed,0xbfc63f44,0x3fffbf44,
0xbf15bec8,0x3f71bffb,0xbff53ffb,0xbfe2bec8,0x3fd5c000,0x3ec8c000,0xbf8e0000,0xbffb0000,0xbec8bf44,0xbf8e3fed,0xbffb3fed,0x3fd53f44,
0xbffb3fb5,0x3fd5bfb5,0xbec83fb5,0xbf8ebfb5,0xbf8e3fed,0xbffb3f44,0x3fd5bf44,0x3ec83fed,0xbfa20000,0xbfff0000,0xbfc64000,0xbe494000,
0xbfe23ffb,0x3ff53ec8,0x3f713ec8,0x3f15bffb,0x3f153f44,0xbfe2bf44,0x3ff5bfed,0xbf713fed,0x3fffbfd5,0x3fc63f8e,0xbe49bf8e,0x3fa2bfd5,
0x4000,0x3fb54000,0x40000000,0x3fb50000,0xc000,0xbfb50000,0xc0000000,0x3fb54000,0x4000,0xbfb5c000,0x40000000,0xbfb50000,
0xc000,0x3fb50000,0xc0000000,0xbfb5c000,0x3fff0000,0x3fa20000,0xbe49c000,0xbfc6c000,0xbff53ec8,0x3fe23ffb,0x3f153ffb,0x3f71bec8,
0x3fe2bf44,0xbf153f44,0xbf71bfed,0x3ff53fed,0xbfc63f8e,0xbfffbfd5,0x3fa23fd5,0xbe493f8e,0xbec8c000,0xbfd5c000,0xbffb0000,0xbf8e0000,
0x3f8e3fed,0x3ec8bf44,0x3fd5bf44,0xbffbbfed,0xbfd5bfb5,0x3ffb3fb5,0xbf8e3fb5,0xbec8bfb5,0x3ffb3f44,0x3f8e3fed,0x3ec8bfed,0x3fd53f44,
0xbff50000,0xbf710000,0x3f154000,0x3fe24000,0x3fa2bf8e,0xbfffbfd5,0xbfc6bfd5,0x3e493f8e,0xbe493fed,0xbfa2bfed,0x3fff3f44,0xbfc6bf44,
0xbf71bffb,0x3f15bec8,0xbfe23ec8,0xbff5bffb,0x3f444000,0x3fed4000,0x3fed0000,0x3f440000,0xbfedbfb5,0x3f443fb5,0xbf443fb5,0x3fed3fb5,
0x3fed0000,0xbf440000,0xbf44c000,0x3fed4000,0xbf443fb5,0xbfedbfb5,0x3fed3fb5,0x3f443fb5,0x3fe20000,0x3f150000,0xbf71c000,0xbff5c000,
0xbe493fd5,0x3fc63f8e,0x3fff3f8e,0xbfa2bfd5,0xbfc6bfed,0x3fff3fed,0xbfa23f44,0xbe49bf44,0x3ff53ec8,0x3fe23ffb,0xbf15bffb,0x3f713ec8,
0xbf8ec000,0xbffbc000,0xbfd50000,0xbec80000,0x3ffb3f44,0xbfd5bfed,0xbec8bfed,0xbf8ebf44,0xbec83fb5,0xbf8ebfb5,0x3ffb3fb5,0xbfd5bfb5,
0xbfd5bfed,0xbec8bf44,0xbf8e3f44,0xbffbbfed,0xbfc60000,0xbe490000,0x3fa24000,0x3fff4000,0xbf71bffb,0xbf15bec8,0xbfe2bec8,0x3ff53ffb,
0x3ff53f44,0xbf71bf44,0xbf15bfed,0x3fe23fed,0x3e493fd5,0xbfa2bf8e,0x3fff3f8e,0x3fc63fd5,0x40004000,0x3fb54000,0x0,0xbfb50000,
0x40004000,0xbfb50000,0x0,0xbfb5c000,0x40004000,0xbfb5c000,0x0,0x3fb50000,0x40004000,0x3fb50000,0x0,0x3fb54000,
0xbfc6bfb5,0xbfffbfb5,0xbfa2bfb5,0x3e49bfb5,0xbfe2bfd5,0x3f15bf8e,0xbf71bf8e,0x3ff53fd5,0xbff5bfed,0x3fe23fed,0xbf15bf44,0xbf713f44,
0xbfffbffb,0xbfa23ec8,0xbe49bec8,0xbfc6bffb,0x3ec80000,0x3fd50000,0x3ffb4000,0x3f8e4000,0x3f8e3f44,0x3ec83fed,0x3fd53fed,0xbffbbf44,
0x3fd53fb5,0xbffbbfb5,0x3f8e3fb5,0x3ec8bfb5,0x3ffb3fed,0x3f8ebf44,0x3ec83f44,0x3fd53fed,0x3f713fb5,0xbf153fb5,0xbfe2bfb5,0xbff5bfb5,
0xbe493ec8,0xbfa2bffb,0xbfffbffb,0x3fc6bec8,0xbfa2bf44,0x3fff3f44,0xbfc6bfed,0x3e493fed,0xbff5bfd5,0xbf713f8e,0xbf15bf8e,0xbfe2bfd5,
0xbfedc000,0xbf44c000,0x3f440000,0x3fed0000,0xbf44bfb5,0x3fed3fb5,0x3fed3fb5,0xbf443fb5,0x3f440000,0xbfed0000,0x3fed4000,0xbf44c000,
0x3fed3fb5,0x3f44bfb5,0x3f443fb5,0x3fed3fb5,0x3ff53fb5,0x3fe23fb5,0x3f153fb5,0xbf713fb5,0x3fc63ffb,0xbfffbec8,0xbfa2bec8,0xbe49bffb,
0xbe493f44,0x3fc6bf44,0xbfffbfed,0x3fa23fed,0xbfe2bf8e,0xbf153fd5,0xbf71bfd5,0xbff5bf8e,0xbf8e0000,0xbffb0000,0xbfd5c000,0xbec8c000,
0xbffbbfed,0x3fd5bf44,0x3ec8bf44,0x3f8e3fed,0xbec8bfb5,0xbf8e3fb5,0x3ffb3fb5,0xbfd5bfb5,0x3fd53f44,0x3ec8bfed,0x3f8e3fed,0x3ffb3f44,
0xbe49bfb5,0x3fa2bfb5,0x3fff3fb5,0x3fc63fb5,0x3ff53f8e,0xbf713fd5,0x3f153fd5,0xbfe2bf8e,0x3f713fed,0x3f15bfed,0xbfe2bf44,0x3ff53f44,
0xbfc6bec8,0xbe493ffb,0xbfa2bffb,0xbfffbec8,0x4000,0xbfb54000,0xc0000000,0xbfb50000,0xc000,0x3fb50000,0x40000000,0xbfb54000,
0x4000,0x3fb5c000,0xc0000000,0x3fb50000,0xc000,0xbfb50000,0x40000000,0x3fb5c000,0xbfa2bfb5,0x3e49bfb5,0x3fc6bfb5,0x3fffbfb5,
0x3f713fd5,0xbff53f8e,0xbfe23f8e,0x3f15bfd5,0xbf15bfed,0xbf713fed,0x3ff5bf44,0xbfe23f44,0x3e493ffb,0x3fc6bec8,0xbfff3ec8,0xbfa23ffb,
0x3ffb0000,0x3f8e0000,0xbec84000,0xbfd54000,0xbfd5bf44,0x3ffbbfed,0x3f8ebfed,0x3ec83f44,0x3f8e3fb5,0x3ec8bfb5,0xbfd53fb5,0x3ffbbfb5,
0xbec8bfed,0xbfd53f44,0x3ffbbf44,0x3f8ebfed,0xbfe23fb5,0xbff53fb5,0xbf71bfb5,0x3f15bfb5,0x3fffbec8,0xbfc63ffb,0xbe493ffb,0xbfa23ec8,
0xbfc6bf44,0x3e493f44,0x3fa2bfed,0xbfff3fed,0x3f153fd5,0x3fe2bf8e,0xbff53f8e,0xbf713fd5,0x3f44c000,0x3fedc000,0x3fed0000,0x3f440000,
0xbfed3fb5,0x3f44bfb5,0xbf44bfb5,0x3fedbfb5,0x3fed0000,0xbf440000,0xbf444000,0x3fedc000,0xbf44bfb5,0xbfed3fb5,0x3fedbfb5,0x3f44bfb5,
0x3f153fb5,0xbf713fb5,0xbff53fb5,0xbfe23fb5,0x3fa2bffb,0x3e493ec8,0x3fc63ec8,0xbfff3ffb,0xbfff3f44,0x3fa2bf44,0x3e49bfed,0xbfc63fed,
0x3f713f8e,0x3ff5bfd5,0xbfe23fd5,0xbf153f8e,0xbfd50000,0xbec80000,0x3f8ec000,0x3ffbc000,0xbec83fed,0xbf8e3f44,0xbffb3f44,0x3fd5bfed,
0x3ffbbfb5,0xbfd53fb5,0x3ec83fb5,0x3f8ebfb5,0xbf8ebf44,0xbffb3fed,0x3fd5bfed,0x3ec8bf44,0x3fffbfb5,0x3fc6bfb5,0x3e493fb5,0xbfa23fb5,
0xbf15bf8e,0x3fe2bfd5,0x3ff5bfd5,0xbf713f8e,0xbfe23fed,0x3ff5bfed,0xbf71bf44,0xbf153f44,0x3fa23ec8,0x3fffbffb,0xbfc63ffb,0xbe493ec8,
0xc0004000,0xbfb54000,0x0,0x3fb50000,0xc0004000,0x3fb50000,0x0,0x3fb5c000,0xc0004000,0x3fb5c000,0x0,0xbfb50000,
0xc0004000,0xbfb50000,0x0,0xbfb54000,0x3fc6bfb5,0x3fffbfb5,0x3fa2bfb5,0xbe49bfb5,0x3fe2bfd5,0xbf15bf8e,0x3f71bf8e,0xbff53fd5,
0x3ff5bfed,0xbfe23fed,0x3f15bf44,0x3f713f44,0x3fffbffb,0x3fa23ec8,0x3e49bec8,0x3fc6bffb,0xbec80000,0xbfd50000,0xbffb4000,0xbf8e4000,
0xbf8e3f44,0xbec83fed,0xbfd53fed,0x3ffbbf44,0xbfd53fb5,0x3ffbbfb5,0xbf8e3fb5,0xbec8bfb5,0xbffb3fed,0xbf8ebf44,0xbec83f44,0xbfd53fed,
0xbf713fb5,0x3f153fb5,0x3fe2bfb5,0x3ff5bfb5,0x3e493ec8,0x3fa2bffb,0x3fffbffb,0xbfc6bec8,0x3fa2bf44,0xbfff3f44,0x3fc6bfed,0xbe493fed,
0x3ff5bfd5,0x3f713f8e,0x3f15bf8e,0x3fe2bfd5,0x3fedc000,0x3f44c000,0xbf440000,0xbfed0000,0x3f44bfb5,0xbfed3fb5,0xbfed3fb5,0x3f443fb5,
0xbf440000,0x3fed0000,0xbfed4000,0x3f44c000,0xbfed3fb5,0xbf44bfb5,0xbf443fb5,0xbfed3fb5,0xbff53fb5,0xbfe23fb5,0xbf153fb5,0x3f713fb5,
0xbfc63ffb,0x3fffbec8,0x3fa2bec8,0x3e49bffb,0x3e493f44,0xbfc6bf44,0x3fffbfed,0xbfa23fed,0x3fe2bf8e,0x3f153fd5,0x3f71bfd5,0x3ff5bf8e,
0x3f8e0000,0x3ffb0000,0x3fd5c000,0x3ec8c000,0x3ffbbfed,0xbfd5bf44,0xbec8bf44,0xbf8e3fed,0x3ec8bfb5,0x3f8e3fb5,0xbffb3fb5,0x3fd5bfb5,
0xbfd53f44,0xbec8bfed,0xbf8e3fed,0xbffb3f44,0x3e49bfb5,0xbfa2bfb5,0xbfff3fb5,0xbfc63fb5,0xbff53f8e,0x3f713fd5,0xbf153fd5,0x3fe2bf8e,
0xbf713fed,0xbf15bfed,0x3fe2bf44,0xbff53f44,0x3fc6bec8,0x3e493ffb,0x3fa2bffb,0x3fffbec8,0x4000,0x3fb54000,0x40000000,0x3fb50000,
0xc000,0xbfb50000,0xc0000000,0x3fb54000,0x4000,0xbfb5c000,0x40000000,0xbfb50000,0xc000,0x3fb50000,0xc0000000,0xbfb5c000,
0x3fa2bfb5,0xbe49bfb5,0xbfc6bfb5,0xbfffbfb5,0xbf713fd5,0x3ff53f8e,0x3fe23f8e,0xbf15bfd5,0x3f15bfed,0x3f713fed,0xbff5bf44,0x3fe23f44,
0xbe493ffb,0xbfc6bec8,0x3fff3ec8,0x3fa23ffb,0xbffb0000,0xbf8e0000,0x3ec84000,0x3fd54000,0x3fd5bf44,0xbffbbfed,0xbf8ebfed,0xbec83f44,
0xbf8e3fb5,0xbec8bfb5,0x3fd53fb5,0xbffbbfb5,0x3ec8bfed,0x3fd53f44,0xbffbbf44,0xbf8ebfed,0x3fe23fb5,0x3ff53fb5,0x3f71bfb5,0xbf15bfb5,
0xbfffbec8,0x3fc63ffb,0x3e493ffb,0x3fa23ec8,0x3fc6bf44,0xbe493f44,0xbfa2bfed,0x3fff3fed,0xbf153fd5,0xbfe2bf8e,0x3ff53f8e,0x3f713fd5,
0xbf44c000,0xbfedc000,0xbfed0000,0xbf440000,0x3fed3fb5,0xbf44bfb5,0x3f44bfb5,0xbfedbfb5,0xbfed0000,0x3f440000,0x3f444000,0xbfedc000,
0x3f44bfb5,0x3fed3fb5,0xbfedbfb5,0xbf44bfb5,0xbf153fb5,0x3f713fb5,0x3ff53fb5,0x3fe23fb5,0xbfa2bffb,0xbe493ec8,0xbfc63ec8,0x3fff3ffb,
0x3fff3f44,0xbfa2bf44,0xbe49bfed,0x3fc63fed,0xbf713f8e,0xbff5bfd5,0x3fe23fd5,0x3f153f8e,0x3fd50000,0x3ec80000,0xbf8ec000,0xbffbc000,
0x3ec83fed,0x3f8e3f44,0x3ffb3f44,0xbfd5bfed,0xbffbbfb5,0x3fd53fb5,0xbec83fb5,0xbf8ebfb5,0x3f8ebf44,0x3ffb3fed,0xbfd5bfed,0xbec8bf44,
0xbfffbfb5,0xbfc6bfb5,0xbe493fb5,0x3fa23fb5,0x3f15bf8e,0xbfe2bfd5,0xbff5bfd5,0x3f713f8e,0x3fe23fed,0xbff5bfed,0x3f71bf44,0x3f153f44,
0xbfa23ec8,0xbfffbffb,0x3fc63ffb,0x3e493ec8,0x80003f80,0x3f800000,0x80003f80,0x3f800000,0x80003f80,0x3f800000,0x80003f80,0x3f800000,
0x80003f80,0x3f800000,0x80003f80,0x3f800000,0x80003f80,0x3f800000,0x80003f80,0x3f800000,0x80003f80,0x3f800000,0x8000bf80,0xbf800000,
0x3f353f35,0x3f35bf35,0xbf35bf35,0xbf353f35,0x3f800000,0xbf80,0xbf800000,0x3f80,0x3f35bf35,0xbf35bf35,0xbf353f35,0x3f353f35,
0x80003f80,0x3f800000,0x80003f80,0x3f800000,0x3f800000,0xbf80,0x3f800000,0xbf80,0x8000bf80,0xbf800000,0x8000bf80,0xbf800000,
0xbf800000,0x3f80,0xbf800000,0x3f80,0x80003f80,0x3f800000,0x8000bf80,0xbf800000,0x3f35bf35,0xbf35bf35,0xbf353f35,0x3f353f35,
0xbf800000,0x3f80,0x3f800000,0xbf80,0x3f353f35,0x3f35bf35,0xbf35bf35,0xbf353f35,0x80003f80,0x3f800000,0x80003f80,0x3f800000,
0x8000bf80,0xbf800000,0x8000bf80,0xbf800000,0x80003f80,0x3f800000,0x80003f80,0x3f800000,0x8000bf80,0xbf800000,0x8000bf80,0xbf800000,
0x80003f80,0x3f800000,0x8000bf80,0xbf800000,0xbf35bf35,0xbf353f35,0x3f353f35,0x3f35bf35,0x3f800000,0xbf80,0xbf800000,0x3f80,
0xbf353f35,0x3f353f35,0x3f35bf35,0xbf35bf35,0x80003f80,0x3f800000,0x80003f80,0x3f800000,0xbf800000,0x3f80,0xbf800000,0x3f80,
0x8000bf80,0xbf800000,0x8000bf80,0xbf800000,0x3f800000,0xbf80,0x3f800000,0xbf80,0x80003f80,0x3f800000,0x8000bf80,0xbf800000,
0xbf353f35,0x3f353f35,0x3f35bf35,0xbf35bf35,0xbf800000,0x3f80,0x3f800000,0xbf80,0xbf35bf35,0xbf353f35,0x3f353f35,0x3f35bf35,
0x3f803f80,0x80008000,0x80008000,0xbf80bf80,0x3f803f80,0x80008000,0x80008000,0xbf80bf80,0x3f803f80,0x80008000,0x80008000,0xbf80bf80,
0x3f803f80,0x80008000,0x80008000,0xbf80bf80,0x3f353f80,0x3f358000,0x3f358000,0xbf35bf80,0xbf350000,0x3f353f80,0x3f353f80,0x3f358000,
0xbf35bf80,0xbf358000,0xbf358000,0x3f353f80,0x3f350000,0xbf35bf80,0xbf35bf80,0xbf358000,0x3f80,0x3f808000,0x3f808000,0x8000bf80,
0xbf80,0xbf808000,0xbf808000,0x80003f80,0x3f80,0x3f808000,0x3f808000,0x8000bf80,0xbf80,0xbf808000,0xbf808000,0x80003f80,
0xbf353f80,0x3f358000,0x3f358000,0x3f35bf80,0x3f350000,0x3f35bf80,0x3f35bf80,0xbf358000,0x3f35bf80,0xbf358000,0xbf358000,0xbf353f80,
0xbf350000,0xbf353f80,0xbf353f80,0x3f358000,0xbf803f80,0x80008000,0x80008000,0x3f80bf80,0xbf803f80,0x80008000,0x80008000,0x3f80bf80,
0xbf803f80,0x80008000,0x80008000,0x3f80bf80,0xbf803f80,0x80008000,0x80008000,0x3f80bf80,0xbf353f80,0xbf358000,0xbf358000,0x3f35bf80,
0x3f350000,0xbf353f80,0xbf353f80,0xbf358000,0x3f35bf80,0x3f358000,0x3f358000,0xbf353f80,0xbf350000,0x3f35bf80,0x3f35bf80,0x3f358000,
0x3f80,0xbf808000,0xbf808000,0x8000bf80,0xbf80,0x3f808000,0x3f808000,0x80003f80,0x3f80,0xbf808000,0xbf808000,0x8000bf80,
0xbf80,0x3f808000,0x3f808000,0x80003f80,0x3f353f80,0xbf358000,0xbf358000,0xbf35bf80,0xbf350000,0xbf35bf80,0xbf35bf80,0x3f358000,
0xbf35bf80,0x3f358000,0x3f358000,0x3f353f80,0x3f350000,0x3f353f80,0x3f353f80,0xbf358000,0x3f800000,0x0,0x3f800000,0x0,
0x3f800000,0x0,0x3f800000,0x0,0x3f800000,0x0,0x3f800000,0x0,0x3f800000,0x0,0x3f800000,0x0,
0x3f800000,0x0,0x3f7fb10f,0xbd48fb30,0x3f7ec46d,0xbdc8bd36,0x3f7d3aac,0xbe164083,0x3f7b14be,0xbe47c5c2,0x3f7853f8,0xbe78cfcc,
0x3f74fa0b,0xbe94a031,0x3f710908,0xbeac7cd4,0x3f800000,0x0,0x3f7ec46d,0xbdc8bd36,0x3f7b14be,0xbe47c5c2,0x3f74fa0b,0xbe94a031,
0x3f6c835e,0xbec3ef15,0x3f61c598,0xbef15aea,0x3f54db31,0xbf0e39da,0x3f45e403,0xbf226799,0x3f800000,0x0,0x3f7d3aac,0xbe164083,
0x3f74fa0b,0xbe94a031,0x3f676bd8,0xbedae880,0x3f54db31,0xbf0e39da,0x3f3daef9,0xbf2beb4a,0x3f226799,0xbf45e403,0x3f039c3d,0xbf5b941a,
0x3f800000,0x0,0x3f7b14be,0xbe47c5c2,0x3f6c835e,0xbec3ef15,0x3f54db31,0xbf0e39da,0x3f3504f3,0xbf3504f3,0x3f0e39da,0xbf54db31,
0x3ec3ef15,0xbf6c835e,0x3e47c5c2,0xbf7b14be,0x3f800000,0x0,0x3f7853f8,0xbe78cfcc,0x3f61c598,0xbef15aea,0x3f3daef9,0xbf2beb4a,
0x3f0e39da,0xbf54db31,0x3eac7cd4,0xbf710908,0x3dc8bd36,0xbf7ec46d,0xbe164083,0xbf7d3aac,0x3f800000,0x0,0x3f74fa0b,0xbe94a031,
0x3f54db31,0xbf0e39da,0x3f226799,0xbf45e403,0x3ec3ef15,0xbf6c835e,0x3dc8bd36,0xbf7ec46d,0xbe47c5c2,0xbf7b14be,0xbef15aea,0xbf61c598,
0x3f800000,0x0,0x3f710908,0xbeac7cd4,0x3f45e403,0xbf226799,0x3f039c3d,0xbf5b941a,0x3e47c5c2,0xbf7b14be,0xbe164083,0xbf7d3aac,
0xbef15aea,0xbf61c598,0xbf3daef9,0xbf2beb4a,0x3f800000,0x0,0x3f800000,0x0,0x3f800000,0x0,0x3f800000,0x0,
0x3f800000,0x0,0x3f800000,0x0,0x3f800000,0x0,0x3f800000,0x0,0x3f6c835e,0xbec3ef15,0x3f676bd8,0xbedae880,
0x3f61c598,0xbef15aea,0x3f5b941a,0xbf039c3d,0x3f54db31,0xbf0e39da,0x3f4d9f02,0xbf187fc0,0x3f45e403,0xbf226799,0x3f3daef9,0xbf2beb4a,
0x3f3504f3,0xbf3504f3,0x3f226799,0xbf45e403,0x3f0e39da,0xbf54db31,0x3ef15aea,0xbf61c598,0x3ec3ef15,0xbf6c835e,0x3e94a031,0xbf74fa0b,
0x3e47c5c2,0xbf7b14be,0x3dc8bd36,0xbf7ec46d,0x3ec3ef15,0xbf6c835e,0x3e78cfcc,0xbf7853f8,0x3dc8bd36,0xbf7ec46d,0xbd48fb30,0xbf7fb10f,
0xbe47c5c2,0xbf7b14be,0xbeac7cd4,0xbf710908,0xbef15aea,0xbf61c598,0xbf187fc0,0xbf4d9f02,0x0,0xbf800000,0xbe47c5c2,0xbf7b14be,
0xbec3ef15,0xbf6c835e,0xbf0e39da,0xbf54db31,0xbf3504f3,0xbf3504f3,0xbf54db31,0xbf0e39da,0xbf6c835e,0xbec3ef15,0xbf7b14be,0xbe47c5c2,
0xbec3ef15,0xbf6c835e,0xbf187fc0,0xbf4d9f02,0xbf45e403,0xbf226799,0xbf676bd8,0xbedae880,0xbf7b14be,0xbe47c5c2,0xbf7fb10f,0x3d48fb30,
0xbf74fa0b,0x3e94a031,0xbf5b941a,0x3f039c3d,0xbf3504f3,0xbf3504f3,0xbf61c598,0xbef15aea,0xbf7b14be,0xbe47c5c2,0xbf7ec46d,0x3dc8bd36,
0xbf6c835e,0x3ec3ef15,0xbf45e403,0x3f226799,0xbf0e39da,0x3f54db31,0xbe94a031,0x3f74fa0b,0xbf6c835e,0xbec3ef15,0xbf7fb10f,0xbd48fb30,
0xbf74fa0b,0x3e94a031,0xbf4d9f02,0x3f187fc0,0xbf0e39da,0x3f54db31,0xbe78cfcc,0x3f7853f8,0x3dc8bd36,0x3f7ec46d,0x3edae880,0x3f676bd8,
0x80003f80,0x3f800000,0x3f800000,0xbf80,0x3ec43f6d,0x3f6dbec4,0x3f6dbec4,0xbec4bf6d,0x3f353f35,0x3f35bf35,0x3f35bf35,0xbf35bf35,
0x3f6d3ec4,0x3ec4bf6d,0x3ec4bf6d,0xbf6dbec4,0x80003f80,0x3f800000,0xbf800000,0x3f80,0x3f6d3ec4,0x3ec4bf6d,0xbec43f6d,0x3f6d3ec4,
0x3f35bf35,0xbf35bf35,0x3f353f35,0x3f35bf35,0xbec4bf6d,0xbf6d3ec4,0x3f6dbec4,0xbec4bf6d,0x80003f80,0x3f800000,0x3f800000,0xbf80,
0x3f6dbec4,0xbec4bf6d,0xbec4bf6d,0xbf6d3ec4,0xbf35bf35,0xbf353f35,0xbf353f35,0x3f353f35,0xbec43f6d,0x3f6d3ec4,0x3f6d3ec4,0x3ec4bf6d,
0x80003f80,0x3f800000,0xbf800000,0x3f80,0x3ec4bf6d,0xbf6dbec4,0x3f6d3ec4,0x3ec4bf6d,0xbf353f35,0x3f353f35,0xbf35bf35,0xbf353f35,
0x3f6dbec4,0xbec4bf6d,0x3ec43f6d,0x3f6dbec4,0x80003f80,0x3f800000,0x3f800000,0xbf80,0xbec4bf6d,0xbf6d3ec4,0xbf6d3ec4,0x3ec43f6d,
0x3f353f35,0x3f35bf35,0x3f35bf35,0xbf35bf35,0xbf6dbec4,0xbec43f6d,0xbec43f6d,0x3f6d3ec4,0x80003f80,0x3f800000,0xbf800000,0x3f80,
0xbf6dbec4,0xbec43f6d,0x3ec4bf6d,0xbf6dbec4,0x3f35bf35,0xbf35bf35,0x3f353f35,0x3f35bf35,0x3ec43f6d,0x3f6dbec4,0xbf6d3ec4,0x3ec43f6d,
0x80003f80,0x3f800000,0x3f800000,0xbf80,0xbf6d3ec4,0x3ec43f6d,0x3ec43f6d,0x3f6dbec4,0xbf35bf35,0xbf353f35,0xbf353f35,0x3f353f35,
0x3ec4bf6d,0xbf6dbec4,0xbf6dbec4,0xbec43f6d,0x80003f80,0x3f800000,0xbf800000,0x3f80,0xbec43f6d,0x3f6d3ec4,0xbf6dbec4,0xbec43f6d,
0xbf353f35,0x3f353f35,0xbf35bf35,0xbf353f35,0xbf6d3ec4,0x3ec43f6d,0xbec4bf6d,0xbf6d3ec4,0x3f803f80,0x80008000,0x80008000,0xbf80bf80,
0x3f803f80,0x80008000,0x80008000,0xbf80bf80,0x3f803f80,0x80008000,0x80008000,0xbf80bf80,0x3f803f80,0x80008000,0x80008000,0xbf80bf80,
0x3ec43f6d,0x3f6d3ec4,0x3f6d3ec4,0xbec4bf6d,0xbf6dbec4,0x3ec43f6d,0x3ec43f6d,0x3f6d3ec4,0xbec4bf6d,0xbf6dbec4,0xbf6dbec4,0x3ec43f6d,
0x3f6d3ec4,0xbec4bf6d,0xbec4bf6d,0xbf6dbec4,0xbf353f35,0x3f353f35,0x3f353f35,0x3f35bf35,0x3f35bf35,0xbf35bf35,0xbf35bf35,0xbf353f35,
0xbf353f35,0x3f353f35,0x3f353f35,0x3f35bf35,0x3f35bf35,0xbf35bf35,0xbf35bf35,0xbf353f35,0xbf6d3ec4,0xbec43f6d,0xbec43f6d,0x3f6dbec4,
0xbec43f6d,0x3f6dbec4,0x3f6dbec4,0x3ec4bf6d,0x3f6dbec4,0x3ec4bf6d,0x3ec4bf6d,0xbf6d3ec4,0x3ec4bf6d,0xbf6d3ec4,0xbf6d3ec4,0xbec43f6d,
0x0,0xbf803f80,0xbf803f80,0x80008000,0x0,0xbf803f80,0xbf803f80,0x80008000,0x0,0xbf803f80,0xbf803f80,0x80008000,
0x0,0xbf803f80,0xbf803f80,0x80008000,0x3f6dbec4,0xbec43f6d,0xbec43f6d,0xbf6d3ec4,0x3ec4bf6d,0x3f6dbec4,0x3f6dbec4,0xbec43f6d,
0xbf6d3ec4,0x3ec4bf6d,0x3ec4bf6d,0x3f6dbec4,0xbec43f6d,0xbf6d3ec4,0xbf6d3ec4,0x3ec4bf6d,0x3f35bf35,0x3f353f35,0x3f353f35,0xbf353f35,
0xbf353f35,0xbf35bf35,0xbf35bf35,0x3f35bf35,0x3f35bf35,0x3f353f35,0x3f353f35,0xbf353f35,0xbf353f35,0xbf35bf35,0xbf35bf35,0x3f35bf35,
0xbec4bf6d,0x3f6d3ec4,0x3f6d3ec4,0x3ec43f6d,0x3f6d3ec4,0x3ec43f6d,0x3ec43f6d,0xbf6dbec4,0x3ec43f6d,0xbf6dbec4,0xbf6dbec4,0xbec4bf6d,
0xbf6dbec4,0xbec4bf6d,0xbec4bf6d,0x3f6d3ec4,0x3f800000,0x0,0x3f7fec43,0xbcc90ab0,0x3f7fb10f,0xbd48fb30,0x3f7f4e6d,0xbd96a905,
0x3f7ec46d,0xbdc8bd36,0x3f7e1324,0xbdfab273,0x3f7d3aac,0xbe164083,0x3f7c3b28,0xbe2f10a2,0x3f800000,0x0,0x3f7f4e6d,0xbd96a905,
0x3f7d3aac,0xbe164083,0x3f79c79d,0xbe605c13,0x3f74fa0b,0xbe94a031,0x3f6ed89e,0xbeb8442a,0x3f676bd8,0xbedae880,0x3f5ebe05,0xbefc5d27,
0x3f800000,0x0,0x3f7e1324,0xbdfab273,0x3f7853f8,0xbe78cfcc,0x3f6ed89e,0xbeb8442a,0x3f61c598,0xbef15aea,0x3f514d3d,0xbf13682a,
0x3f3daef9,0xbf2beb4a,0x3f273656,0xbf41d870,0x3f800000,0x0,0x3f7c3b28,0xbe2f10a2,0x3f710908,0xbeac7cd4,0x3f5ebe05,0xbefc5d27,
0x3f45e403,0xbf226799,0x3f273656,0xbf41d870,0x3f039c3d,0xbf5b941a,0x3eb8442a,0xbf6ed89e,0x3f800000,0x0,0x3f79c79d,0xbe605c13,
0x3f676bd8,0xbedae880,0x3f49d112,0xbf1d7fd1,0x3f226799,0xbf45e403,0x3ee63375,0xbf64aa59,0x3e78cfcc,0xbf7853f8,0x3cc90ab0,0xbf7fec43,
0x3f800000,0x0,0x3f76ba07,0xbe888e93,0x3f5b941a,0xbf039c3d,0x3f3085bb,0xbf396842,0x3ef15aea,0xbf61c598,0x3e605c13,0xbf79c79d,
0xbd48fb30,0xbf7fb10f,0xbea09ae5,0xbf731447,0x3f800000,0x0,0x3f731447,0xbea09ae5,0x3f4d9f02,0xbf187fc0,0x3f13682a,0xbf514d3d,
0x3e94a031,0xbf74fa0b,0xbcc90ab0,0xbf7fec43,0xbeac7cd4,0xbf710908,0xbf1d7fd1,0xbf49d112,0x3f800000,0x0,0x3f6ed89e,0xbeb8442a,
0x3f3daef9,0xbf2beb4a,0x3ee63375,0xbf64aa59,0x3dc8bd36,0xbf7ec46d,0xbe888e93,0xbf76ba07,0xbf187fc0,0xbf4d9f02,0xbf584853,0xbf08f59b,
0x3f7b14be,0xbe47c5c2,0x3f79c79d,0xbe605c13,0x3f7853f8,0xbe78cfcc,0x3f76ba07,0xbe888e93,0x3f74fa0b,0xbe94a031,0x3f731447,0xbea09ae5,
0x3f710908,0xbeac7cd4,0x3f6ed89e,0xbeb8442a,0x3f54db31,0xbf0e39da,0x3f49d112,0xbf1d7fd1,0x3f3daef9,0xbf2beb4a,0x3f3085bb,0xbf396842,
0x3f226799,0xbf45e403,0x3f13682a,0xbf514d3d,0x3f039c3d,0xbf5b941a,0x3ee63375,0xbf64aa59,0x3f0e39da,0xbf54db31,0x3ee63375,0xbf64aa59,
0x3eac7cd4,0xbf710908,0x3e605c13,0xbf79c79d,0x3dc8bd36,0xbf7ec46d,0xbcc90ab0,0xbf7fec43,0xbe164083,0xbf7d3aac,0xbe888e93,0xbf76ba07,
0x3e47c5c2,0xbf7b14be,0x3cc90ab0,0xbf7fec43,0xbe164083,0xbf7d3aac,0xbea09ae5,0xbf731447,0xbef15aea,0xbf61c598,0xbf1d7fd1,0xbf49d112,
0xbf3daef9,0xbf2beb4a,0xbf584853,0xbf08f59b,0xbe47c5c2,0xbf7b14be,0xbecf7bca,0xbf6a09a7,0xbf187fc0,0xbf4d9f02,0xbf41d870,0xbf273656,
0xbf61c598,0xbef15aea,0xbf76ba07,0xbe888e93,0xbf7fb10f,0xbd48fb30,0xbf7c3b28,0x3e2f10a2,0xbf0e39da,0xbf54db31,0xbf41d870,0xbf273656,
0xbf676bd8,0xbedae880,0xbf7c3b28,0xbe2f10a2,0xbf7ec46d,0x3dc8bd36,0xbf6ed89e,0x3eb8442a,0xbf4d9f02,0x3f187fc0,0xbf1d7fd1,0x3f49d112,
0xbf54db31,0xbf0e39da,0xbf76ba07,0xbe888e93,0xbf7fb10f,0x3d48fb30,0xbf6ed89e,0x3eb8442a,0xbf45e403,0x3f226799,0xbf08f59b,0x3f584853,
0xbe78cfcc,0x3f7853f8,0x3d96a905,0x3f7f4e6d,0xbf7b14be,0xbe47c5c2,0xbf7c3b28,0x3e2f10a2,0xbf5b941a,0x3f039c3d,0xbf1d7fd1,0x3f49d112,
0xbe94a031,0x3f74fa0b,0x3d96a905,0x3f7f4e6d,0x3edae880,0x3f676bd8,0x3f396842,0x3f3085bb,0x80003f80,0x80003f80,0x80003f80,0x80003f80,
0x80003f80,0x80003f80,0x80003f80,0x80003f80,0x80003f80,0x80003f80,0x80003f80,0x80003f80,0x80003f80,0x80003f80,0x80003f80,0x80003f80,
0x3f800000,0x3f800000,0x3f800000,0x3f800000,0x3f800000,0x3f800000,0x3f800000,0x3f800000,0x3f800000,0x3f800000,0x3f800000,0x3f800000,
0x3f800000,0x3f800000,0x3f800000,0x3f800000,0x80003f80,0x3f353f35,0x80003f80,0x3f353f35,0x3f800000,0x3f35bf35,0x3f800000,0x3f35bf35,
0x8000bf80,0xbf35bf35,0x8000bf80,0xbf35bf35,0xbf800000,0xbf353f35,0xbf800000,0xbf353f35,0x3f800000,0x3f35bf35,0x3f800000,0x3f35bf35,
0xbf80,0xbf35bf35,0xbf80,0xbf35bf35,0xbf800000,0xbf353f35,0xbf800000,0xbf353f35,0x3f80,0x3f353f35,0x3f80,0x3f353f35,
0x80003f80,0x3f800000,0x80003f80,0x3f800000,0x8000bf80,0xbf800000,0x8000bf80,0xbf800000,0x80003f80,0x3f800000,0x80003f80,0x3f800000,
0x8000bf80,0xbf800000,0x8000bf80,0xbf800000,0x3f800000,0xbf80,0x3f800000,0xbf80,0xbf800000,0x3f80,0xbf800000,0x3f80,
0x3f800000,0xbf80,0x3f800000,0xbf80,0xbf800000,0x3f80,0xbf800000,0x3f80,0x80003f80,0x3f35bf35,0x80003f80,0x3f35bf35,
0xbf800000,0x3f353f35,0xbf800000,0x3f353f35,0x8000bf80,0xbf353f35,0x8000bf80,0xbf353f35,0x3f800000,0xbf35bf35,0x3f800000,0xbf35bf35,
0x3f800000,0xbf35bf35,0x3f800000,0xbf35bf35,0x3f80,0x3f35bf35,0x3f80,0x3f35bf35,0xbf800000,0x3f353f35,0xbf800000,0x3f353f35,
0xbf80,0xbf353f35,0xbf80,0xbf353f35,0x80003f80,0x3ec43f6d,0x8000bf80,0xbec4bf6d,0x3f353f35,0x3f6d3ec4,0xbf35bf35,0xbf6dbec4,
0x3f800000,0x3f6dbec4,0xbf800000,0xbf6d3ec4,0x3f35bf35,0x3ec4bf6d,0xbf353f35,0xbec43f6d,0x3f800000,0x3f6dbec4,0xbf800000,0xbf6d3ec4,
0x3f35bf35,0x3ec4bf6d,0xbf353f35,0xbec43f6d,0xbf80,0xbec4bf6d,0x3f80,0x3ec43f6d,0xbf35bf35,0xbf6dbec4,0x3f353f35,0x3f6d3ec4,
0x80003f80,0x3f6d3ec4,0x8000bf80,0xbf6dbec4,0x3f35bf35,0xbec4bf6d,0xbf353f35,0x3ec43f6d,0xbf800000,0xbec43f6d,0x3f800000,0x3ec4bf6d,
0x3f353f35,0x3f6dbec4,0xbf35bf35,0xbf6d3ec4,0x3f800000,0x3ec4bf6d,0xbf800000,0xbec43f6d,0xbf35bf35,0xbf6d3ec4,0x3f353f35,0x3f6dbec4,
0x3f80,0x3f6d3ec4,0xbf80,0xbf6dbec4,0x3f35bf35,0xbec4bf6d,0xbf353f35,0x3ec43f6d,0x80003f80,0x3f6dbec4,0x8000bf80,0xbf6d3ec4,
0xbf35bf35,0xbec43f6d,0x3f353f35,0x3ec4bf6d,0x3f800000,0xbec4bf6d,0xbf800000,0x3ec43f6d,0xbf353f35,0x3f6d3ec4,0x3f35bf35,0xbf6dbec4,
0x3f800000,0xbec4bf6d,0xbf800000,0x3ec43f6d,0xbf353f35,0x3f6d3ec4,0x3f35bf35,0xbf6dbec4,0xbf80,0xbf6d3ec4,0x3f80,0x3f6dbec4,
0x3f353f35,0x3ec4bf6d,0xbf35bf35,0xbec43f6d,0x80003f80,0x3ec4bf6d,0x8000bf80,0xbec43f6d,0xbf353f35,0x3f6dbec4,0x3f35bf35,0xbf6d3ec4,
0xbf800000,0x3f6d3ec4,0x3f800000,0xbf6dbec4,0xbf35bf35,0x3ec43f6d,0x3f353f35,0xbec4bf6d,0x3f800000,0xbf6dbec4,0xbf800000,0x3f6d3ec4,
0x3f353f35,0xbec4bf6d,0xbf35bf35,0x3ec43f6d,0x3f80,0x3ec4bf6d,0xbf80,0xbec43f6d,0xbf353f35,0x3f6dbec4,0x3f35bf35,0xbf6d3ec4,
0x80003f80,0x8000bf80,0x80003f80,0x8000bf80,0x80003f80,0x8000bf80,0x80003f80,0x8000bf80,0x80003f80,0x8000bf80,0x80003f80,0x8000bf80,
0x80003f80,0x8000bf80,0x80003f80,0x8000bf80,0x3f800000,0xbf800000,0x3f800000,0xbf800000,0x3f800000,0xbf800000,0x3f800000,0xbf800000,
0x3f800000,0xbf800000,0x3f800000,0xbf800000,0x3f800000,0xbf800000,0x3f800000,0xbf800000,0x80003f80,0xbf35bf35,0x80003f80,0xbf35bf35,
0x3f800000,0xbf353f35,0x3f800000,0xbf353f35,0x8000bf80,0x3f353f35,0x8000bf80,0x3f353f35,0xbf800000,0x3f35bf35,0xbf800000,0x3f35bf35,
0x3f800000,0xbf353f35,0x3f800000,0xbf353f35,0xbf80,0x3f353f35,0xbf80,0x3f353f35,0xbf800000,0x3f35bf35,0xbf800000,0x3f35bf35,
0x3f80,0xbf35bf35,0x3f80,0xbf35bf35,0x80003f80,0xbf800000,0x80003f80,0xbf800000,0x8000bf80,0x3f800000,0x8000bf80,0x3f800000,
0x80003f80,0xbf800000,0x80003f80,0xbf800000,0x8000bf80,0x3f800000,0x8000bf80,0x3f800000,0x3f800000,0x3f80,0x3f800000,0x3f80,
0xbf800000,0xbf80,0xbf800000,0xbf80,0x3f800000,0x3f80,0x3f800000,0x3f80,0xbf800000,0xbf80,0xbf800000,0xbf80,
0x80003f80,0xbf353f35,0x80003f80,0xbf353f35,0xbf800000,0xbf35bf35,0xbf800000,0xbf35bf35,0x8000bf80,0x3f35bf35,0x8000bf80,0x3f35bf35,
0x3f800000,0x3f353f35,0x3f800000,0x3f353f35,0x3f800000,0x3f353f35,0x3f800000,0x3f353f35,0x3f80,0xbf353f35,0x3f80,0xbf353f35,
0xbf800000,0xbf35bf35,0xbf800000,0xbf35bf35,0xbf80,0x3f35bf35,0xbf80,0x3f35bf35,0x80003f80,0xbec4bf6d,0x8000bf80,0x3ec43f6d,
0x3f353f35,0xbf6dbec4,0xbf35bf35,0x3f6d3ec4,0x3f800000,0xbf6d3ec4,0xbf800000,0x3f6dbec4,0x3f35bf35,0xbec43f6d,0xbf353f35,0x3ec4bf6d,
0x3f800000,0xbf6d3ec4,0xbf800000,0x3f6dbec4,0x3f35bf35,0xbec43f6d,0xbf353f35,0x3ec4bf6d,0xbf80,0x3ec43f6d,0x3f80,0xbec4bf6d,
0xbf35bf35,0x3f6d3ec4,0x3f353f35,0xbf6dbec4,0x80003f80,0xbf6dbec4,0x8000bf80,0x3f6d3ec4,0x3f35bf35,0x3ec43f6d,0xbf353f35,0xbec4bf6d,
0xbf800000,0x3ec4bf6d,0x3f800000,0xbec43f6d,0x3f353f35,0xbf6d3ec4,0xbf35bf35,0x3f6dbec4,0x3f800000,0xbec43f6d,0xbf800000,0x3ec4bf6d,
0xbf35bf35,0x3f6dbec4,0x3f353f35,0xbf6d3ec4,0x3f80,0xbf6dbec4,0xbf80,0x3f6d3ec4,0x3f35bf35,0x3ec43f6d,0xbf353f35,0xbec4bf6d,
0x80003f80,0xbf6d3ec4,0x8000bf80,0x3f6dbec4,0xbf35bf35,0x3ec4bf6d,0x3f353f35,0xbec43f6d,0x3f800000,0x3ec43f6d,0xbf800000,0xbec4bf6d,
0xbf353f35,0xbf6dbec4,0x3f35bf35,0x3f6d3ec4,0x3f800000,0x3ec43f6d,0xbf800000,0xbec4bf6d,0xbf353f35,0xbf6dbec4,0x3f35bf35,0x3f6d3ec4,
0xbf80,0x3f6dbec4,0x3f80,0xbf6d3ec4,0x3f353f35,0xbec43f6d,0xbf35bf35,0x3ec4bf6d,0x80003f80,0xbec43f6d,0x8000bf80,0x3ec4bf6d,
0xbf353f35,0xbf6d3ec4,0x3f35bf35,0x3f6dbec4,0xbf800000,0xbf6dbec4,0x3f800000,0x3f6d3ec4,0xbf35bf35,0xbec4bf6d,0x3f353f35,0x3ec43f6d,
0x3f800000,0x3f6d3ec4,0xbf800000,0xbf6dbec4,0x3f353f35,0x3ec43f6d,0xbf35bf35,0xbec4bf6d,0x3f80,0xbec43f6d,0xbf80,0x3ec4bf6d,
0xbf353f35,0xbf6d3ec4,0x3f35bf35,0x3f6dbec4,
};
constexpr int TB_F = 0, TB_E = 512, TB_P2 = 1024;

enum { C_EP = 0, C_Z1 = 32, C_Z2 = 96, C_H3 = 128, C_U = 160, C_X = 288, C_TOTAL = 512 };
struct Scratch {
  unsigned cnt[C_TOTAL];
  uint32_t moda[8 * 2 * D_];
  uint32_t mod[4 * D_ + 256];
  uint32_t z1[120 * 5120];
  uint32_t z2[128 * 4800];
  uint8_t h3[32 * 18 * 4096];
  uint8_t u[72 * D_ * 128];
};
__device__ __align__(1024) Scratch g_s;

constexpr int HOLDA = 5;
constexpr int X1K = 10;
constexpr int NV1 = 12;
constexpr int NV2 = 20;
constexpr int W0N = 3;
constexpr int TRK0 = 50;
constexpr int TRKC = 350;
constexpr int HD1 = 150;
constexpr int EH = 7;

struct Maps { CUtensorMap z1, z2[2], w1a, w1b, h3, w2, wf[4], wm; };
struct Params {
  const __nv_bfloat16 *x, *c, *wmod;
  Scratch* s;
  const uint4* tab;
  const __nv_bfloat16 *wr, *wi, *w1, *w2, *b1, *b2;
  uint32_t* out;
};

__device__ __forceinline__ uint32_t smem_u32(const void* p) { return (uint32_t)__cvta_generic_to_shared(p); }
__device__ __forceinline__ void mbar_init(uint32_t b, int c) { asm volatile("mbarrier.init.shared::cta.b64 [%0], %1;" ::"r"(b), "r"(c)); }
__device__ __forceinline__ void mbar_expect(uint32_t b, int bytes) { asm volatile("mbarrier.arrive.expect_tx.shared::cta.b64 _, [%0], %1;" ::"r"(b), "r"(bytes) : "memory"); }
__device__ __forceinline__ void mbar_arrive(uint32_t b) { asm volatile("mbarrier.arrive.shared::cta.b64 _, [%0];" ::"r"(b) : "memory"); }
__device__ __forceinline__ void mbar_wait(uint32_t b, int ph) {
  asm volatile("{\n.reg .pred p;\n.reg .u32 it;\nmov.u32 it, 0;\nW:\nmbarrier.try_wait.parity.shared::cta.b64 p, [%0], %1;\n"
               "@p bra.uni D;\nadd.u32 it, it, 1;\nsetp.lt.u32 p, it, 0x400000;\n@p bra.uni W;\ntrap;\nD:\n}" ::"r"(b), "r"(ph) : "memory");
}
__device__ __forceinline__ uint32_t mbar_test(uint32_t b, int ph) {
  uint32_t ok;
  asm volatile("{\n.reg .pred p;\nmbarrier.test_wait.parity.shared::cta.b64 p, [%1], %2;\nselp.u32 %0, 1, 0, p;\n}\n" : "=r"(ok) : "r"(b), "r"(ph) : "memory");
  return ok;
}
__device__ __forceinline__ void tma2d(uint32_t dst, const CUtensorMap* m, int c0, int c1, uint32_t bar) {
  asm volatile("cp.async.bulk.tensor.2d.shared::cluster.global.mbarrier::complete_tx::bytes [%0], [%1, {%3, %4}], [%2];" ::"r"(dst), "l"(m), "r"(bar), "r"(c0), "r"(c1) : "memory");
}
__device__ __forceinline__ uint64_t pol_ef() { uint64_t p; asm("createpolicy.fractional.L2::evict_first.b64 %0, 1.0;" : "=l"(p)); return p; }
__device__ __forceinline__ void tma3d_ef(uint32_t dst, const CUtensorMap* m, int c1, int c2, uint32_t bar) {
  asm volatile("cp.async.bulk.tensor.3d.shared::cluster.global.mbarrier::complete_tx::bytes.L2::cache_hint [%0], [%1, {%3, %4, %5}], [%2], %6;" ::"r"(dst), "l"(m), "r"(bar), "r"(0), "r"(c1), "r"(c2), "l"(pol_ef()) : "memory");
}
__device__ __forceinline__ void tma4d_ef(uint32_t dst, const CUtensorMap* m, int c1, int c2, int c3, uint32_t bar) {
  asm volatile("cp.async.bulk.tensor.4d.shared::cluster.global.mbarrier::complete_tx::bytes.L2::cache_hint [%0], [%1, {%3, %7, %4, %5}], [%2], %6;" ::"r"(dst), "l"(m), "r"(bar), "r"(0), "r"(c2), "r"(c3), "l"(pol_ef()), "r"(c1) : "memory");
}
__device__ __forceinline__ void bulk_ld(uint32_t dst, const void* src, int bytes, uint32_t bar) {
  asm volatile("cp.async.bulk.shared::cluster.global.mbarrier::complete_tx::bytes [%0], [%1], %2, [%3];" ::"r"(dst), "l"(src), "r"(bytes), "r"(bar) : "memory");
}
__device__ __forceinline__ void bulk_st(void* dst, uint32_t src, int bytes) {
  asm volatile("cp.async.bulk.global.shared::cta.bulk_group [%0], [%1], %2;" ::"l"(dst), "r"(src), "r"(bytes) : "memory");
}
__device__ __forceinline__ void tma_st2d(const CUtensorMap* m, uint32_t src, int c0, int c1) {
  asm volatile("cp.async.bulk.tensor.2d.global.shared::cta.bulk_group [%0, {%2, %3}], [%1];" ::"l"(m), "r"(src), "r"(c0), "r"(c1) : "memory");
}
__device__ __forceinline__ void tma_st3d(const CUtensorMap* m, uint32_t src, int c0, int c1, int c2) {
  asm volatile("cp.async.bulk.tensor.3d.global.shared::cta.bulk_group [%0, {%2, %3, %4}], [%1];" ::"l"(m), "r"(src), "r"(c0), "r"(c1), "r"(c2) : "memory");
}
__device__ __forceinline__ void bulk_commit_wait() {
  asm volatile("cp.async.bulk.commit_group;" ::: "memory");
  asm volatile("cp.async.bulk.wait_group 0;" ::: "memory");
}
__device__ __forceinline__ void prefetch_l2(const void* p, int bytes) {
  asm volatile("cp.async.bulk.prefetch.L2.global [%0], %1;" ::"l"(p), "r"(bytes) : "memory");
}
__device__ __forceinline__ void wg_fence() { asm volatile("wgmma.fence.sync.aligned;" ::: "memory"); }
__device__ __forceinline__ void wg_commit() { asm volatile("wgmma.commit_group.sync.aligned;" ::: "memory"); }
template <int N> __device__ __forceinline__ void wg_wait() { asm volatile("wgmma.wait_group.sync.aligned %0;" ::"n"(N) : "memory"); }
template <int N> __device__ __forceinline__ void reg_fence(float (&d)[N]) {
#pragma unroll
  for (int i = 0; i < N; i++) asm volatile("" : "+f"(d[i])::"memory");
}
__device__ __forceinline__ void fence_async_smem() { asm volatile("fence.proxy.async.shared::cta;" ::: "memory"); }
__device__ __forceinline__ void fence_async_glb() { asm volatile("fence.proxy.async.global;" ::: "memory"); }
__device__ __forceinline__ uint32_t ld_rlx(const void* p) { uint32_t v; asm volatile("ld.relaxed.gpu.global.b32 %0, [%1];" : "=r"(v) : "l"(p) : "memory"); return v; }
__device__ __forceinline__ uint2 ld_rlx2(const void* p) { uint2 v; asm volatile("ld.relaxed.gpu.global.v2.b32 {%0,%1}, [%2];" : "=r"(v.x), "=r"(v.y) : "l"(p) : "memory"); return v; }
__device__ __forceinline__ uint4 ld_rlx4(const void* p) { uint4 v; asm volatile("ld.relaxed.gpu.global.v4.b32 {%0,%1,%2,%3}, [%4];" : "=r"(v.x), "=r"(v.y), "=r"(v.z), "=r"(v.w) : "l"(p) : "memory"); return v; }
__device__ __forceinline__ uint32_t ld_nc(const void* p) { uint32_t v; asm volatile("ld.global.nc.L1::no_allocate.b32 %0, [%1];" : "=r"(v) : "l"(p) : "memory"); return v; }
__device__ __forceinline__ uint4 ld_nc4(const void* p) { uint4 v; asm volatile("ld.global.nc.v4.b32 {%0,%1,%2,%3}, [%4];" : "=r"(v.x), "=r"(v.y), "=r"(v.z), "=r"(v.w) : "l"(p) : "memory"); return v; }
__device__ __forceinline__ uint32_t lds(uint32_t a) { uint32_t v; asm volatile("ld.shared.b32 %0, [%1];" : "=r"(v) : "r"(a) : "memory"); return v; }
__device__ __forceinline__ uint2 lds2(uint32_t a) { uint2 v; asm volatile("ld.shared.v2.b32 {%0,%1}, [%2];" : "=r"(v.x), "=r"(v.y) : "r"(a) : "memory"); return v; }
__device__ __forceinline__ void lds2_if(int on, uint2& v, uint32_t a) { asm volatile("{\n.reg .pred p;\nsetp.ne.u32 p, %3, 0;\n@p ld.shared.v2.b32 {%0,%1}, [%2];\n}" : "+r"(v.x), "+r"(v.y) : "r"(a), "r"(on) : "memory"); }
__device__ __forceinline__ uint4 lds4(uint32_t a) { uint4 v; asm volatile("ld.shared.v4.b32 {%0,%1,%2,%3}, [%4];" : "=r"(v.x), "=r"(v.y), "=r"(v.z), "=r"(v.w) : "r"(a) : "memory"); return v; }
__device__ __forceinline__ float lds_bf(uint32_t a) { uint32_t v; asm volatile("ld.shared.u16 %0, [%1];" : "=r"(v) : "r"(a) : "memory"); return __uint_as_float(v << 16); }
__device__ __forceinline__ void sts(uint32_t a, uint32_t v) { asm volatile("st.shared.b32 [%0], %1;" ::"r"(a), "r"(v) : "memory"); }
__device__ __forceinline__ void sts2(uint32_t a, uint32_t v0, uint32_t v1) { asm volatile("st.shared.v2.b32 [%0], {%1,%2};" ::"r"(a), "r"(v0), "r"(v1) : "memory"); }
__device__ __forceinline__ void sts4(uint32_t a, uint32_t v0, uint32_t v1, uint32_t v2, uint32_t v3) { asm volatile("st.shared.v4.b32 [%0], {%1,%2,%3,%4};" ::"r"(a), "r"(v0), "r"(v1), "r"(v2), "r"(v3) : "memory"); }
__device__ __forceinline__ void bar_sync(int id, int n) { asm volatile("bar.sync %0, %1;" ::"r"(id), "r"(n) : "memory"); }
__device__ __forceinline__ void bar_arrive(int id, int n) { asm volatile("bar.arrive %0, %1;" ::"r"(id), "r"(n) : "memory"); }
__device__ __forceinline__ void red_add(unsigned* p, unsigned v) { asm volatile("red.relaxed.gpu.global.add.u32 [%0], %1;" ::"l"(p), "r"(v) : "memory"); }
__device__ __forceinline__ bool any(bool p) { return __any_sync(0xffffffffu, p); }
__device__ __forceinline__ void pause(unsigned clks) {
  asm volatile("{\n.reg .pred p;\n.reg .u32 a, b;\nmov.u32 a, %%clock;\nW:\nmov.u32 b, %%clock;\nsub.u32 b, b, a;\nsetp.lt.s32 p, b, %0;\n@p bra.uni W;\n}" ::"r"(clks) : "memory");
}
__device__ __forceinline__ void red_bf16x8(uint32_t* p, uint32_t a, uint32_t b, uint32_t c, uint32_t d) {
  asm volatile("red.relaxed.gpu.global.add.noftz.v4.bf16x2 [%0], {%1,%2,%3,%4};" ::"l"(p), "r"(a), "r"(b), "r"(c), "r"(d) : "memory");
}
__device__ __forceinline__ void red_bf16x4(uint32_t* p, uint32_t a, uint32_t b) {
  asm volatile("red.relaxed.gpu.global.add.noftz.v2.bf16x2 [%0], {%1,%2};" ::"l"(p), "r"(a), "r"(b) : "memory");
}
constexpr int SPIN_MAX = 1 << 20;
__device__ __forceinline__ uint32_t ld_acq(const void* p) { uint32_t v; asm volatile("ld.acquire.gpu.global.b32 %0, [%1];" : "=r"(v) : "l"(p) : "memory"); return v; }
template <bool ACQ = false> __device__ __forceinline__ void wait_cnt(const unsigned* p, unsigned target) {
  int it = 0;
  while (any((int)((ACQ ? ld_acq(p) : ld_rlx(p)) - target) < 0) && ++it < SPIN_MAX) {}
}
__device__ __forceinline__ uint32_t pack_bf16(float lo, float hi) { uint32_t r; asm("cvt.rn.bf16x2.f32 %0, %1, %2;" : "=r"(r) : "f"(hi), "f"(lo)); return r; }
__device__ __forceinline__ float bf_lo(uint32_t v) { return __uint_as_float(v << 16); }
__device__ __forceinline__ float bf_hi(uint32_t v) { return __uint_as_float(v & 0xffff0000u); }
__device__ __forceinline__ uint32_t hmul2(uint32_t a, uint32_t b) { uint32_t r; asm("mul.rn.bf16x2 %0, %1, %2;" : "=r"(r) : "r"(a), "r"(b)); return r; }
__device__ __forceinline__ uint32_t hfma2(uint32_t a, uint32_t b, uint32_t c) { uint32_t r; asm("fma.rn.bf16x2 %0, %1, %2, %3;" : "=r"(r) : "r"(a), "r"(b), "r"(c)); return r; }
__device__ __forceinline__ float rbf(float x) { uint32_t r; asm("cvt.rn.bf16x2.f32 %0, %1, %2;" : "=r"(r) : "f"(x), "f"(0.0f)); return __uint_as_float(r); }
__device__ __forceinline__ void stmatrix4(uint32_t a, uint32_t r0, uint32_t r1, uint32_t r2, uint32_t r3) {
  asm volatile("stmatrix.sync.aligned.m8n8.x4.shared.b16 [%0], {%1,%2,%3,%4};" ::"r"(a), "r"(r0), "r"(r1), "r"(r2), "r"(r3) : "memory");
}
__device__ __forceinline__ void stmatrix2(uint32_t a, uint32_t r0, uint32_t r1) {
  asm volatile("stmatrix.sync.aligned.m8n8.x2.shared.b16 [%0], {%1,%2};" ::"r"(a), "r"(r0), "r"(r1) : "memory");
}
__device__ __forceinline__ uint32_t movm(uint32_t a) { uint32_t r; asm("movmatrix.sync.aligned.m8n8.trans.b16 %0, %1;" : "=r"(r) : "r"(a)); return r; }
template <bool ACC> __device__ __forceinline__ void mma16(float* d, uint32_t a0, uint32_t a1, uint32_t a2, uint32_t a3, uint32_t b0, uint32_t b1) {
  if (ACC) asm("mma.sync.aligned.m16n8k16.row.col.f32.bf16.bf16.f32 {%0,%1,%2,%3}, {%4,%5,%6,%7}, {%8,%9}, {%0,%1,%2,%3};"
               : "+f"(d[0]), "+f"(d[1]), "+f"(d[2]), "+f"(d[3]) : "r"(a0), "r"(a1), "r"(a2), "r"(a3), "r"(b0), "r"(b1));
  else asm("mma.sync.aligned.m16n8k16.row.col.f32.bf16.bf16.f32 {%0,%1,%2,%3}, {%4,%5,%6,%7}, {%8,%9}, {%10,%10,%10,%10};"
           : "=f"(d[0]), "=f"(d[1]), "=f"(d[2]), "=f"(d[3]) : "r"(a0), "r"(a1), "r"(a2), "r"(a3), "r"(b0), "r"(b1), "f"(0.f));
}
__device__ __forceinline__ uint32_t pin(uint32_t v) { uint32_t r; asm volatile("shfl.sync.bfly.b32 %0, %1, 0, 31, 0xffffffff;" : "=r"(r) : "r"(v)); return r; }
template <class T> __device__ __forceinline__ T* pin(T* p) {
  const uint64_t a = reinterpret_cast<uint64_t>(p);
  return reinterpret_cast<T*>((uint64_t)pin((uint32_t)a) | ((uint64_t)pin((uint32_t)(a >> 32)) << 32));
}
__device__ __forceinline__ uint32_t upin(uint32_t v) { return __shfl_sync(0xffffffffu, v, 0); }
template <class T> __device__ __forceinline__ T* upin(T* p) {
  const uint64_t a = reinterpret_cast<uint64_t>(p);
  return reinterpret_cast<T*>((uint64_t)upin((uint32_t)a) | ((uint64_t)upin((uint32_t)(a >> 32)) << 32));
}
__device__ __forceinline__ int lane_id() { int v; asm volatile("mov.u32 %0, %%laneid;" : "=r"(v)); return v; }
__device__ __forceinline__ bool elect() {
  uint32_t p;
  asm volatile("{\n.reg .pred P;\nelect.sync _|P, 0xffffffff;\nselp.u32 %0, 1, 0, P;\n}" : "=r"(p));
  return p;
}
__device__ __forceinline__ uint32_t set_tag(uint32_t w, uint32_t tag) { uint32_t r; asm("lop3.b32 %0, %1, 0xfffffffe, %2, 0xea;" : "=r"(r) : "r"(w), "r"(tag)); return r; }
__device__ __forceinline__ uint32_t bitsel(uint32_t w, uint32_t m, uint32_t o) { uint32_t r; asm("lop3.b32 %0, %1, %2, %3, 0xe2;" : "=r"(r) : "r"(w), "r"(m), "r"(o)); return r; }
__device__ __forceinline__ uint32_t or3(uint32_t a, uint32_t b, uint32_t c) { uint32_t r; asm("lop3.b32 %0, %1, %2, %3, 0xfe;" : "=r"(r) : "r"(a), "r"(b), "r"(c)); return r; }
__device__ __forceinline__ uint32_t diff2(uint32_t a, uint32_t b, uint32_t tag) { uint32_t r; asm("lop3.b32 %0, %1, %2, %3, 0x7e;" : "=r"(r) : "r"(a), "r"(b), "r"(tag)); return r; }
__device__ __forceinline__ float2 cmul(float2 a, float2 b) { return make_float2(a.x * b.x - a.y * b.y, a.x * b.y + a.y * b.x); }

template<int TB> __device__ __forceinline__ void wgmma_ss_160_0(float (&d)[96], uint32_t al, uint32_t ah, uint32_t bl, uint32_t bh) {
  asm volatile("{\n.reg .b64 da, db;\nmov.b64 da, {%80, %81};\nmov.b64 db, {%82, %83};\n"
    "wgmma.mma_async.sync.aligned.m64n160k16.f32.bf16.bf16 {%0,%1,%2,%3,%4,%5,%6,%7,%8,%9,%10,%11,%12,%13,%14,%15,%16,%17,%18,%19,%20,%21,%22,%23,%24,%25,%26,%27,%28,%29,%30,%31,%32,%33,%34,%35,%36,%37,%38,%39,%40,%41,%42,%43,%44,%45,%46,%47,%48,%49,%50,%51,%52,%53,%54,%55,%56,%57,%58,%59,%60,%61,%62,%63,%64,%65,%66,%67,%68,%69,%70,%71,%72,%73,%74,%75,%76,%77,%78,%79}, da, db, 1, 1, 1, 1, %84;\n}\n"
    : "+f"(d[0]),"+f"(d[1]),"+f"(d[2]),"+f"(d[3]),"+f"(d[4]),"+f"(d[5]),"+f"(d[6]),"+f"(d[7]),"+f"(d[8]),"+f"(d[9]),"+f"(d[10]),"+f"(d[11]),"+f"(d[12]),"+f"(d[13]),"+f"(d[14]),"+f"(d[15]),"+f"(d[16]),"+f"(d[17]),"+f"(d[18]),"+f"(d[19]),"+f"(d[20]),"+f"(d[21]),"+f"(d[22]),"+f"(d[23]),"+f"(d[24]),"+f"(d[25]),"+f"(d[26]),"+f"(d[27]),"+f"(d[28]),"+f"(d[29]),"+f"(d[30]),"+f"(d[31]),"+f"(d[32]),"+f"(d[33]),"+f"(d[34]),"+f"(d[35]),"+f"(d[36]),"+f"(d[37]),"+f"(d[38]),"+f"(d[39]),"+f"(d[40]),"+f"(d[41]),"+f"(d[42]),"+f"(d[43]),"+f"(d[44]),"+f"(d[45]),"+f"(d[46]),"+f"(d[47]),"+f"(d[48]),"+f"(d[49]),"+f"(d[50]),"+f"(d[51]),"+f"(d[52]),"+f"(d[53]),"+f"(d[54]),"+f"(d[55]),"+f"(d[56]),"+f"(d[57]),"+f"(d[58]),"+f"(d[59]),"+f"(d[60]),"+f"(d[61]),"+f"(d[62]),"+f"(d[63]),"+f"(d[64]),"+f"(d[65]),"+f"(d[66]),"+f"(d[67]),"+f"(d[68]),"+f"(d[69]),"+f"(d[70]),"+f"(d[71]),"+f"(d[72]),"+f"(d[73]),"+f"(d[74]),"+f"(d[75]),"+f"(d[76]),"+f"(d[77]),"+f"(d[78]),"+f"(d[79])
    : "r"(al), "r"(ah), "r"(bl), "r"(bh), "n"(TB));
}
template<int TB> __device__ __forceinline__ void wgmma_ss_144_0(float (&d)[96], uint32_t al, uint32_t ah, uint32_t bl, uint32_t bh) {
  asm volatile("{\n.reg .b64 da, db;\nmov.b64 da, {%72, %73};\nmov.b64 db, {%74, %75};\n"
    "wgmma.mma_async.sync.aligned.m64n144k16.f32.bf16.bf16 {%0,%1,%2,%3,%4,%5,%6,%7,%8,%9,%10,%11,%12,%13,%14,%15,%16,%17,%18,%19,%20,%21,%22,%23,%24,%25,%26,%27,%28,%29,%30,%31,%32,%33,%34,%35,%36,%37,%38,%39,%40,%41,%42,%43,%44,%45,%46,%47,%48,%49,%50,%51,%52,%53,%54,%55,%56,%57,%58,%59,%60,%61,%62,%63,%64,%65,%66,%67,%68,%69,%70,%71}, da, db, 1, 1, 1, 1, %76;\n}\n"
    : "+f"(d[0]),"+f"(d[1]),"+f"(d[2]),"+f"(d[3]),"+f"(d[4]),"+f"(d[5]),"+f"(d[6]),"+f"(d[7]),"+f"(d[8]),"+f"(d[9]),"+f"(d[10]),"+f"(d[11]),"+f"(d[12]),"+f"(d[13]),"+f"(d[14]),"+f"(d[15]),"+f"(d[16]),"+f"(d[17]),"+f"(d[18]),"+f"(d[19]),"+f"(d[20]),"+f"(d[21]),"+f"(d[22]),"+f"(d[23]),"+f"(d[24]),"+f"(d[25]),"+f"(d[26]),"+f"(d[27]),"+f"(d[28]),"+f"(d[29]),"+f"(d[30]),"+f"(d[31]),"+f"(d[32]),"+f"(d[33]),"+f"(d[34]),"+f"(d[35]),"+f"(d[36]),"+f"(d[37]),"+f"(d[38]),"+f"(d[39]),"+f"(d[40]),"+f"(d[41]),"+f"(d[42]),"+f"(d[43]),"+f"(d[44]),"+f"(d[45]),"+f"(d[46]),"+f"(d[47]),"+f"(d[48]),"+f"(d[49]),"+f"(d[50]),"+f"(d[51]),"+f"(d[52]),"+f"(d[53]),"+f"(d[54]),"+f"(d[55]),"+f"(d[56]),"+f"(d[57]),"+f"(d[58]),"+f"(d[59]),"+f"(d[60]),"+f"(d[61]),"+f"(d[62]),"+f"(d[63]),"+f"(d[64]),"+f"(d[65]),"+f"(d[66]),"+f"(d[67]),"+f"(d[68]),"+f"(d[69]),"+f"(d[70]),"+f"(d[71])
    : "r"(al), "r"(ah), "r"(bl), "r"(bh), "n"(TB));
}
template<int TB> __device__ __forceinline__ void wgmma_ss_96_0(float (&d)[96], uint32_t al, uint32_t ah, uint32_t bl, uint32_t bh) {
  asm volatile("{\n.reg .b64 da, db;\nmov.b64 da, {%48, %49};\nmov.b64 db, {%50, %51};\n"
    "wgmma.mma_async.sync.aligned.m64n96k16.f32.bf16.bf16 {%0,%1,%2,%3,%4,%5,%6,%7,%8,%9,%10,%11,%12,%13,%14,%15,%16,%17,%18,%19,%20,%21,%22,%23,%24,%25,%26,%27,%28,%29,%30,%31,%32,%33,%34,%35,%36,%37,%38,%39,%40,%41,%42,%43,%44,%45,%46,%47}, da, db, 1, 1, 1, 1, %52;\n}\n"
    : "+f"(d[0]),"+f"(d[1]),"+f"(d[2]),"+f"(d[3]),"+f"(d[4]),"+f"(d[5]),"+f"(d[6]),"+f"(d[7]),"+f"(d[8]),"+f"(d[9]),"+f"(d[10]),"+f"(d[11]),"+f"(d[12]),"+f"(d[13]),"+f"(d[14]),"+f"(d[15]),"+f"(d[16]),"+f"(d[17]),"+f"(d[18]),"+f"(d[19]),"+f"(d[20]),"+f"(d[21]),"+f"(d[22]),"+f"(d[23]),"+f"(d[24]),"+f"(d[25]),"+f"(d[26]),"+f"(d[27]),"+f"(d[28]),"+f"(d[29]),"+f"(d[30]),"+f"(d[31]),"+f"(d[32]),"+f"(d[33]),"+f"(d[34]),"+f"(d[35]),"+f"(d[36]),"+f"(d[37]),"+f"(d[38]),"+f"(d[39]),"+f"(d[40]),"+f"(d[41]),"+f"(d[42]),"+f"(d[43]),"+f"(d[44]),"+f"(d[45]),"+f"(d[46]),"+f"(d[47])
    : "r"(al), "r"(ah), "r"(bl), "r"(bh), "n"(TB));
}
template<int TB> __device__ __forceinline__ void wgmma_ss_96_48(float (&d)[96], uint32_t al, uint32_t ah, uint32_t bl, uint32_t bh) {
  asm volatile("{\n.reg .b64 da, db;\nmov.b64 da, {%48, %49};\nmov.b64 db, {%50, %51};\n"
    "wgmma.mma_async.sync.aligned.m64n96k16.f32.bf16.bf16 {%0,%1,%2,%3,%4,%5,%6,%7,%8,%9,%10,%11,%12,%13,%14,%15,%16,%17,%18,%19,%20,%21,%22,%23,%24,%25,%26,%27,%28,%29,%30,%31,%32,%33,%34,%35,%36,%37,%38,%39,%40,%41,%42,%43,%44,%45,%46,%47}, da, db, 1, 1, 1, 1, %52;\n}\n"
    : "+f"(d[48]),"+f"(d[49]),"+f"(d[50]),"+f"(d[51]),"+f"(d[52]),"+f"(d[53]),"+f"(d[54]),"+f"(d[55]),"+f"(d[56]),"+f"(d[57]),"+f"(d[58]),"+f"(d[59]),"+f"(d[60]),"+f"(d[61]),"+f"(d[62]),"+f"(d[63]),"+f"(d[64]),"+f"(d[65]),"+f"(d[66]),"+f"(d[67]),"+f"(d[68]),"+f"(d[69]),"+f"(d[70]),"+f"(d[71]),"+f"(d[72]),"+f"(d[73]),"+f"(d[74]),"+f"(d[75]),"+f"(d[76]),"+f"(d[77]),"+f"(d[78]),"+f"(d[79]),"+f"(d[80]),"+f"(d[81]),"+f"(d[82]),"+f"(d[83]),"+f"(d[84]),"+f"(d[85]),"+f"(d[86]),"+f"(d[87]),"+f"(d[88]),"+f"(d[89]),"+f"(d[90]),"+f"(d[91]),"+f"(d[92]),"+f"(d[93]),"+f"(d[94]),"+f"(d[95])
    : "r"(al), "r"(ah), "r"(bl), "r"(bh), "n"(TB));
}
__device__ __forceinline__ void wgmma_rs_72(float (&d)[36], uint32_t a0, uint32_t a1, uint32_t a2, uint32_t a3, uint32_t bl, uint32_t bh, int sd) {
  asm volatile("{\n.reg .pred p;\n.reg .b64 db;\nsetp.ne.b32 p, %42, 0;\nmov.b64 db, {%40, %41};\n"
    "wgmma.mma_async.sync.aligned.m64n72k16.f32.bf16.bf16 {%0,%1,%2,%3,%4,%5,%6,%7,%8,%9,%10,%11,%12,%13,%14,%15,%16,%17,%18,%19,%20,%21,%22,%23,%24,%25,%26,%27,%28,%29,%30,%31,%32,%33,%34,%35}, {%36,%37,%38,%39}, db, p, 1, 1, 1;\n}\n"
    : "+f"(d[0]),"+f"(d[1]),"+f"(d[2]),"+f"(d[3]),"+f"(d[4]),"+f"(d[5]),"+f"(d[6]),"+f"(d[7]),"+f"(d[8]),"+f"(d[9]),"+f"(d[10]),"+f"(d[11]),"+f"(d[12]),"+f"(d[13]),"+f"(d[14]),"+f"(d[15]),"+f"(d[16]),"+f"(d[17]),"+f"(d[18]),"+f"(d[19]),"+f"(d[20]),"+f"(d[21]),"+f"(d[22]),"+f"(d[23]),"+f"(d[24]),"+f"(d[25]),"+f"(d[26]),"+f"(d[27]),"+f"(d[28]),"+f"(d[29]),"+f"(d[30]),"+f"(d[31]),"+f"(d[32]),"+f"(d[33]),"+f"(d[34]),"+f"(d[35])
    : "r"(a0), "r"(a1), "r"(a2), "r"(a3), "r"(bl), "r"(bh), "r"(sd));
}
__device__ __forceinline__ void wgmma_rs_48(float (&d)[24], uint32_t a0, uint32_t a1, uint32_t a2, uint32_t a3, uint32_t bl, uint32_t bh, int sd) {
  asm volatile("{\n.reg .pred p;\n.reg .b64 db;\nsetp.ne.b32 p, %30, 0;\nmov.b64 db, {%28, %29};\n"
    "wgmma.mma_async.sync.aligned.m64n48k16.f32.bf16.bf16 {%0,%1,%2,%3,%4,%5,%6,%7,%8,%9,%10,%11,%12,%13,%14,%15,%16,%17,%18,%19,%20,%21,%22,%23}, {%24,%25,%26,%27}, db, p, 1, 1, 1;\n}\n"
    : "+f"(d[0]),"+f"(d[1]),"+f"(d[2]),"+f"(d[3]),"+f"(d[4]),"+f"(d[5]),"+f"(d[6]),"+f"(d[7]),"+f"(d[8]),"+f"(d[9]),"+f"(d[10]),"+f"(d[11]),"+f"(d[12]),"+f"(d[13]),"+f"(d[14]),"+f"(d[15]),"+f"(d[16]),"+f"(d[17]),"+f"(d[18]),"+f"(d[19]),"+f"(d[20]),"+f"(d[21]),"+f"(d[22]),"+f"(d[23])
    : "r"(a0), "r"(a1), "r"(a2), "r"(a3), "r"(bl), "r"(bh), "r"(sd));
}
template<int N,int OFF,int TB> __device__ __forceinline__ void wgmma_ss(float (&d)[96], uint32_t al, uint32_t ah, uint32_t bl, uint32_t bh) {
  if constexpr (N==160 && OFF==0) wgmma_ss_160_0<TB>(d, al, ah, bl, bh);
  else if constexpr (N==144 && OFF==0) wgmma_ss_144_0<TB>(d, al, ah, bl, bh);
  else if constexpr (N==96 && OFF==0) wgmma_ss_96_0<TB>(d, al, ah, bl, bh);
  else if constexpr (N==96 && OFF==48) wgmma_ss_96_48<TB>(d, al, ah, bl, bh);
}

__device__ __forceinline__ void dft3(float2& a, float2& b, float2& c) {
  const float s = 0.86602540378443864676f;
  float2 t = make_float2(b.x + c.x, b.y + c.y), d = make_float2(b.x - c.x, b.y - c.y);
  float2 m = make_float2(fmaf(-0.5f, t.x, a.x), fmaf(-0.5f, t.y, a.y));
  a = make_float2(a.x + t.x, a.y + t.y);
  b = make_float2(fmaf(s, d.y, m.x), fmaf(-s, d.x, m.y));
  c = make_float2(fmaf(-s, d.y, m.x), fmaf(s, d.x, m.y));
}
__device__ __forceinline__ void dft9(float2 (&x)[9]) {
  const float2 w1 = make_float2(0.76604444311897803520f, -0.64278760968653932632f);
  const float2 w2 = make_float2(0.17364817766693034885f, -0.98480775301220805937f);
  const float2 w4 = make_float2(-0.93969262078590838405f, -0.34202014332566873304f);
  dft3(x[0], x[3], x[6]); dft3(x[1], x[4], x[7]); dft3(x[2], x[5], x[8]);
  x[4] = cmul(x[4], w1); x[7] = cmul(x[7], w2); x[5] = cmul(x[5], w2); x[8] = cmul(x[8], w4);
  dft3(x[0], x[1], x[2]); dft3(x[3], x[4], x[5]); dft3(x[6], x[7], x[8]);
  float2 t;
  t = x[1]; x[1] = x[3]; x[3] = t;
  t = x[2]; x[2] = x[6]; x[6] = t;
  t = x[5]; x[5] = x[7]; x[7] = t;
}

__device__ __forceinline__ uint32_t* mod_ptr(Scratch* sc, int u, int t128) {
  const int i = t128 & 15;
  return u < 72 ? sc->moda + (t128 >> 4) * (2 * D_) + 16 * u + 2 * (i & 7) + (i >> 3) : sc->mod + 16 * (u - 72) + i;
}
__device__ __forceinline__ void mod_unit(Scratch* sc, int u, int t128, uint32_t sw_, uint32_t bar, int ph, uint32_t rb, uint32_t tag) {
  const int w = t128 >> 5, l = t128 & 31;
  uint32_t b[18];
#pragma unroll
  for (int i = 0; i < 18; i++) b[i] = lds(red + 512 + (72 * w + 4 * i + (l & 3)) * 4);
  const uint32_t sa = pin(sw_ + (144 * w + (l & 7) + 8 * (l >> 4)) * 32 + (((l >> 3) ^ (l >> 2)) & 1) * 16);
  const uint32_t sr = pin(rb + (l >> 2) * 16 + w * 4);
  uint32_t* const dst = pin(mod_ptr(sc, u, t128));
  const int kind = u / 36;
  const float mul = __uint_as_float(pin(__float_as_uint(kind == 0 ? 16.0f : 1.0f))), add = __uint_as_float(pin(__float_as_uint(kind == 1 || kind == 4 ? 1.0f : 0.0f)));
  mbar_wait(bar, ph);
  float d[3][4];
#pragma unroll
  for (int i = 0; i < 9; i++) {
    uint32_t a0, a1, a2, a3;
    asm volatile("ldmatrix.sync.aligned.m8n8.x4.trans.shared.b16 {%0,%1,%2,%3}, [%4];" : "=r"(a0), "=r"(a1), "=r"(a2), "=r"(a3) : "r"(sa + i * 512) : "memory");
    if (i < 3) mma16<false>(d[i], a0, a1, a2, a3, b[2 * i], b[2 * i + 1]);
    else mma16<true>(d[i % 3], a0, a1, a2, a3, b[2 * i], b[2 * i + 1]);
  }
  if ((l & 3) == 0) { sts(sr, __float_as_uint(d[0][0] + d[1][0] + d[2][0])); sts(sr + 128, __float_as_uint(d[0][2] + d[1][2] + d[2][2])); }
  bar_sync(4, 128);
  const uint4 v = lds4(rb + (l & 15) * 16);
  const float m = rbf(fmaf(rbf((__uint_as_float(v.x) + __uint_as_float(v.y)) + (__uint_as_float(v.z) + __uint_as_float(v.w))), mul, add));
  if (u < 72 || t128 < 16) *dst = __float_as_uint(m) | tag;
}

__device__ __forceinline__ float rsq(float x) { float r; asm("rsqrt.approx.ftz.f32 %0, %1;" : "=f"(r) : "f"(x)); return r; }
__device__ __forceinline__ void ln_stats2(const float (&a)[18], const float (&b)[18], float sc, float& oa, float& ra, float& ob, float& rb) {
  float v[4] = {0.f, 0.f, 0.f, 0.f}, w[4] = {0.f, 0.f, 0.f, 0.f};
#pragma unroll
  for (int i = 0; i < 18; i += 2) {
    v[0] += a[i]; v[1] = fmaf(a[i], a[i], v[1]); v[2] += b[i]; v[3] = fmaf(b[i], b[i], v[3]);
    w[0] += a[i + 1]; w[1] = fmaf(a[i + 1], a[i + 1], w[1]); w[2] += b[i + 1]; w[3] = fmaf(b[i + 1], b[i + 1], w[3]);
  }
#pragma unroll
  for (int e = 0; e < 4; e++) v[e] += w[e];
#pragma unroll
  for (int o = 16; o; o >>= 1) {
#pragma unroll
    for (int e = 0; e < 4; e++) v[e] += __shfl_xor_sync(0xffffffffu, v[e], o);
  }
  const float ma = v[0] * (1.0f / D_), mb = v[2] * (1.0f / D_);
  ra = sc * rsq(fmaxf(fmaf(-ma, ma, v[1] * (1.0f / D_)), 0.f) + 1e-5f);
  rb = sc * rsq(fmaxf(fmaf(-mb, mb, v[3] * (1.0f / D_)), 0.f) + 1e-5f);
  oa = -ma * ra; ob = -mb * rb;
}

__device__ __forceinline__ void ln_stats1(const float (&a)[18], float sc, float& oa, float& ra) {
  float v[3] = {a[0], a[1], a[2]}, w[3] = {a[0] * a[0], a[1] * a[1], a[2] * a[2]};
#pragma unroll
  for (int i = 3; i < 18; i++) { v[i % 3] += a[i]; w[i % 3] = fmaf(a[i], a[i], w[i % 3]); }
  float s = v[0] + v[1] + v[2], q = w[0] + w[1] + w[2];
#pragma unroll
  for (int o = 16; o; o >>= 1) { s += __shfl_xor_sync(0xffffffffu, s, o); q += __shfl_xor_sync(0xffffffffu, q, o); }
  const float m = s * (1.0f / D_);
  ra = sc * rsq(fmaxf(fmaf(-m, m, q * (1.0f / D_)), 0.f) + 1e-5f);
  oa = -m * ra;
}

__device__ __forceinline__ float tmat(int c, int q, int j) {
  const int ph = q == 1 ? 1024 * j : (q >> 1) * (c + 128 * j) + 512 * (q & 1);
  return __cosf((float)(((ph + 1024) & 2047) - 1024) * (6.283185307179586f / 2048.0f));
}
__device__ __forceinline__ uint32_t line_off(int k1, int kap, int pi, int f) {
  int kd = 64 * k1 + 9 * kap;
  if (kap == 0 && k1 > 4) kd -= 288;
  if (kd >= D_) kd -= D_;
  return pi * 2400 + ((min(kd, D_ - kd) ^ f) << 3);
}

struct Ring { uint32_t st, ph; };
template <bool G2, class T> __device__ __forceinline__ void ring_next(T& st, T& ph) {
  if (++st == NST) st = 0;
  ph ^= ((G2 ? 0xDu : 0x1u) >> st) & 1;
}
__device__ __forceinline__ void arrive_if(uint32_t a, uint32_t p) {
  asm volatile("{\n.reg .pred p;\nsetp.ne.u32 p, %1, 0;\n@p mbarrier.arrive.shared::cta.b64 _, [%0];\n}" ::"r"(a), "r"(p) : "memory");
}
template <int NA> __device__ __forceinline__ void reg_fence_n(float (&d)[96]) {
#pragma unroll
  for (int i = 0; i < NA; i++) asm volatile("" : "+f"(d[i])::"memory");
}
template <int MODE>
__device__ __forceinline__ void gemm_main(float (&acc)[96], uint32_t da0, uint32_t da1, uint32_t db0, int wg, Ring& rg,
                                          bool rows, int J, uint32_t* x1p, const uint32_t (&xr)[18]) {
  constexpr int NKB = MODE == 3 ? 36 : 32;
  constexpr uint32_t HA = 0x40000040u, HB = MODE == 3 ? 0xC0000010u : 0x80000020u;
  constexpr uint32_t KA = 2048 >> 4, KB = (MODE == 3 ? 512 : 1024) >> 4;
  constexpr int NA = MODE == 3 ? 72 : MODE == 1 ? 96 : 80;
  const uint32_t t = threadIdx.x & 127;
  const uint32_t eb = full0 + 8 * NST;
  constexpr uint32_t SP = (MODE == 3 ? STAGE2 : STAGE) >> 4;
  uint32_t pb = 0, prel = 0, ok = 0, sn = rg.st * SP;
  int n = MODE != 3 ? X1K + 2 * wg : wg ? NKB - J : NKB, nh = 0, ng = MODE == 3 && !wg;
#pragma unroll 1
  for (int pass = MODE == 3 ? 0 : -1;; pass++) {
#pragma unroll 1
    do {
      mbar_wait(full0 + 8 * rg.st, rg.ph);
#pragma unroll 1
      do {
      const uint32_t so = sn, cb = eb + 8 * rg.st;
      reg_fence_n<NA>(acc);
      if (MODE == 1 && wg) {
        wg_fence();
#pragma unroll
        for (int k = 0; k < 4; k++) wgmma_ss<96, 48, 1>(acc, da1 + so + k * KA, HA, db0 + so + k * KB, HB);
        wg_commit();
      }
      wg_fence();
#pragma unroll
      for (int k = 0; k < 4; k++) {
        if (k == 2) asm volatile("{\n.reg .pred p;\nsetp.eq.s32 p, %0, %1;\n@p bar.arrive 1, 256;\n}" ::"r"(n), "r"(ng) : "memory");
        if (k == 1 && MODE != 1) { wg_commit(); wg_wait<1>(); arrive_if(pb, prel); }
        if (k == 2) { ring_next<MODE == 3>(rg.st, rg.ph); sn = rg.st * SP; ok = mbar_test(full0 + 8 * rg.st, rg.ph); }
        if (MODE == 0) wgmma_ss<160, 0, 1>(acc, da0 + so + k * KA, HA, db0 + so + k * KB, HB);
        else if (MODE == 3) wgmma_ss<144, 0, 1>(acc, da0 + so + k * KA, HA, db0 + so + k * KB, HB);
        else wgmma_ss<96, 0, 1>(acc, da0 + so + k * KA, HA, db0 + so + k * KB, HB);
      }
      wg_commit();
      if (MODE == 1) { wg_wait<1>(); arrive_if(pb, prel); }
      reg_fence_n<NA>(acc);
      pb = cb; prel = t == 0 && (MODE != 0 || n != nh);
      } while (--n && ok);
    } while (n);
    if (pass == wg) break;
    if (MODE != 3 && pass < 0) {
      if (rows) {
#pragma unroll
        for (int i = 0; i < 9; i++) { x1p[32 * i] = xr[i]; x1p[512 * 288 + 32 * i] = xr[9 + i]; }
      }
      n = NKB - X1K - (J + 2) * wg;
      if (!wg) { ng = 1; if (J < NST) nh = NST; }
      continue;
    }
    wg_wait<0>();
    arrive_if(pb, prel);
    prel = 0;
    n = J;
    if (MODE == 0 && J < NST) bar_arrive(11, 256);
    bar_sync(1, 256);
  }
  if (MODE == 0 && J < NST && !wg) bar_sync(11, 256);
  wg_wait<0>();
  reg_fence_n<NA>(acc);
  if (MODE != 3) arrive_if(pb, prel);
}

constexpr float GK1 = 2.0f * 0.7978845608028654f, GK3 = 8.0f * 0.044715f * 0.7978845608028654f;

__device__ __forceinline__ int kb2_order(int i) { const int wv = i / 6; return 6 * (i - 6 * wv) + ((0x431250 >> (4 * wv)) & 7); }

__device__ __forceinline__ int kb2_pos(int kb) { const int hf = kb >= 36, k = kb - 36 * hf, gr = k / 6; return 64 * hf + gr + 6 * ((0x154230 >> (4 * (k - 6 * gr))) & 7); }

__device__ __forceinline__ void wait_flags(const unsigned* p, int idx, unsigned target, uint32_t& ready) {
  int it = 0;
  while (!((ready >> idx) & 1) && it++ < SPIN_MAX) ready = __ballot_sync(0xffffffffu, (int)(ld_rlx(p) - target) >= 0);
}

enum { B_FULL = 0, B_EMPTY = 6, B_S4 = 12, B_S5, B_LAND, B_FLT = B_LAND + 6, B_Z1, B_Z2, B_GO, B_X, B_WM, B_NUM, B_W0 = B_NUM };

__global__ void __launch_bounds__(NTHR, 1)
fused_kernel(const Params p, const __grid_constant__ Maps maps) {
  extern __shared__ __align__(1024) uint8_t smem_raw[];
  const int bx = blockIdx.x, cta = bx < 112 || bx >= 130 ? bx : bx < 114 ? bx + 16 : bx - 2;
  const int tid = threadIdx.x, t128 = tid & 127;
  const int wp = __shfl_sync(0xffffffffu, tid >> 5, 0), wg = wp >> 2;
  const int l = tid & 31, g = l >> 2, t = l & 3;
  Scratch* const sc = p.s;
  const bool rows = cta < 128;
  const int mu = rows ? cta + 4 : cta - 128;
  const int R = mu - 12;

  uint32_t xr[18];
  uint32_t cv[3];
  const unsigned ep0 = ld_rlx(&sc->cnt[C_EP + l]);
  if (wg == 2) {
#pragma unroll
    for (int i = 0; i < 3; i++) cv[i] = ld_nc(reinterpret_cast<const uint32_t*>(p.c) + min(t128 + 128 * i, 287));
    if (wp == 9 && l < 9 && rows) {
      const int h = 9 * cta + l;
      prefetch_l2(reinterpret_cast<const uint8_t*>(p.wmod) + (size_t)(h >> 1) * (12 * D_) + (h & 1) * (2 * D_), 2 * D_);
    }
    if (tid == 256 && mu < 72) {
      mbar_init(full0 + 8 * B_W0, 1);
      fence_async_smem();
      mbar_expect(full0 + 8 * B_W0, 18432);
#pragma unroll 1
      for (int i = 0; i < 3; i++) tma2d(sbase + O_P2 + i * 6144, &maps.wm, 16 * mu, 192 * i, full0 + 8 * B_W0);
    }
    __syncwarp();
#pragma unroll 1
    for (int u = mu < 72 ? mu : 72 + mu; u < 216; u += u < 72 ? 72 : NCTA) if (u < 72 || t128 < 16) *mod_ptr(sc, u, t128) = 0;
    if (wp == 11 && smem_u32(smem_raw) != sbase) __trap();
    if (wp >= 10 && elect()) {
#pragma unroll 1
      for (int i = wp - 10; i < B_NUM; i += 2) mbar_init(full0 + 8 * i, i == B_FLT ? 4 : i == B_WM ? 3 : i < B_S4 ? 2 : 1);
      fence_async_smem();
    }
    __syncwarp();
  } else if (rows) {
    const uint32_t* xs = reinterpret_cast<const uint32_t*>(p.x) + (size_t)(cta + 128 * ((wp & 3) + 8 * wg)) * 288 + l;
#pragma unroll
    for (int i = 0; i < 9; i++) { xr[i] = ld_nc(xs + 32 * i); xr[9 + i] = ld_nc(xs + 512 * 288 + 32 * i); }
  }
  if (tid == 64 && cta == NCTA - 1) prefetch_l2(p.tab, sizeof(T_TAB));
  __syncwarp();
  auto tag_of = [](unsigned e) { return (e & 0x7fffu) | 0x8000u; };
  const int kap = 8 * ((wp & 3) ^ (wg & 1)) + g;
  uint32_t tb[4], sb1[3], lo[9];
#pragma unroll
  for (int i = 0; i < 4; i++) tb[i] = pin(pack_bf16(tmat(cta, 8 * (i >> 1) + g, t + 8 * (i & 1)), tmat(cta, 8 * (i >> 1) + g, t + 8 * (i & 1) + 4)));
#pragma unroll
  for (int i = 0; i < 3; i++) {
    const int d = 48 * wp + 16 * i + (l & 15);
    sb1[i] = pin(sbase + O_B1 + (l >> 4) * 9216 + (d % 9) * 1024 + (d & 63) * 16);
  }
#pragma unroll
  for (int k1 = 0; k1 < 9; k1++) lo[k1] = pin(sbase + O_Z1 + line_off(k1, kap, 4 * wg + t, cta & 3));
  const uint32_t snt = pin(sbase + O_NRM + ((l & 7) + 8 * (l >> 4)) * 1168 + (48 * wp + (l & 8)) * 2), sn = pin(sbase + O_NRM + wp * 2336 + l * 4);
  const uint32_t smask = pin(t ? 0u : 0xffff0000u);
  const uint32_t* const mp = pin(sc->moda + (cta >> 4) * (2 * D_) + 48 * wp + 2 * g);
  const uint4* const ftab = pin(p.tab + TB_F + (t128 ^ (wg << 5)));

  if (wg == 2) {
#pragma unroll
    for (int i = 0; i < 3; i++) {
      const float c0 = bf_lo(cv[i]), c1 = bf_hi(cv[i]);
      sts(red + 512 + min(t128 + 128 * i, 287) * 4, pack_bf16(__fdividef(c0, 1.0f + __expf(-c0)), __fdividef(c1, 1.0f + __expf(-c1))));
    }
    if (t128 == 0) sts(full0 + 248, ep0 + 1);
    if (wp == 9 && l < 11) asm volatile("prefetch.tensormap [%0];" ::"l"(&maps.z1 + l) : "memory");
    bar_sync(4, 128);
    if (mu < 72) {
      mod_unit(sc, mu, t128, sbase + O_P2, full0 + 8 * B_W0, 0, red, tag_of(upin(ep0) + 1));
    }
  }
  const int pi = R / 15, col0 = 20 * (R - 15 * pi);
  const int xu = DF_ * pi + col0, xv = DF_ * (pi ? 16 - pi : 8) + col0;
  auto load_filter = [&](int a) {
    const int x = (a & 1) ? xv : xu;
    const bool wide = (x & 15) > 12;
    mbar_expect(full0 + 8 * B_FLT, wide ? 12288 : 8192);
    tma2d(sbase + O_RAW + a * 12288, &maps.wf[a & 2], x & ~15, 0, full0 + 8 * B_FLT);
    if (wide) tma2d(sbase + O_RAW + a * 12288 + 8192, &maps.wf[(a & 2) + 1], (x & ~15) + 32, 0, full0 + 8 * B_FLT);
  };
  uint4 af[4];
  if (rows) {
    uint2 ms[3], mc[3];
    auto load_mod = [&](uint32_t o = 0) {
#pragma unroll
      for (int i = 0; i < 3; i++) { ms[i] = ld_rlx2(mp + 2 * o + 16 * i); mc[i] = ld_rlx2(mp + 2 * o + D_ + 16 * i); }
    };
    if (wg < 2) {
      float a[18], b[18];
#pragma unroll
      for (int i = 0; i < 9; i++) { a[2 * i] = bf_lo(xr[i]); a[2 * i + 1] = bf_hi(xr[i]); b[2 * i] = bf_lo(xr[9 + i]); b[2 * i + 1] = bf_hi(xr[9 + i]); }
      float oa, ra, ob, rb;
      ln_stats2(a, b, 1.0f, oa, ra, ob, rb);
      load_mod((__float_as_uint(ra) | __float_as_uint(rb)) >> 31);
#pragma unroll
      for (int i = 0; i < 9; i++) {
        sts(sn + i * 128, pack_bf16(fmaf(a[2 * i], ra, oa), fmaf(a[2 * i + 1], ra, oa)));
        sts(sn + 1168 + i * 128, pack_bf16(fmaf(b[2 * i], rb, ob), fmaf(b[2 * i + 1], rb, ob)));
      }
      bar_arrive(10, NTHR);
#pragma unroll
      for (int kk = 0; kk < 4; kk++) af[kk] = ld_nc4(ftab + kk * 128);
      bar_sync(1, 256);
    } else {
      bar_sync(10, NTHR);
      load_mod();
      if (wp >= 10 && elect()) prefetch_l2(reinterpret_cast<const uint8_t*>(wp == 10 ? p.wr : p.wi) + cta * 9248, 9248);
      __syncwarp();
    }
    float rs[3][8];
#pragma unroll
    for (int i = 0; i < 3; i++) {
      uint32_t a0, a1, a2, a3;
      asm volatile("ldmatrix.sync.aligned.m8n8.x4.trans.shared.b16 {%0,%1,%2,%3}, [%4];" : "=r"(a0), "=r"(a1), "=r"(a2), "=r"(a3)
                   : "r"(snt + 32 * i) : "memory");
      mma16<false>(&rs[i][0], a0, a1, a2, a3, tb[0], tb[1]);
      mma16<false>(&rs[i][4], a0, a1, a2, a3, tb[2], tb[3]);
    }
    const uint32_t tag16 = tag_of(upin(ep0) + 1), tag1 = tag16 & 1;
    {
      int it = 0;
#pragma unroll 1
      while (true) {
        uint32_t bad = 0;
#pragma unroll
        for (int i = 0; i < 3; i++) bad |= diff2(ms[i].x, ms[i].y, tag16) | diff2(mc[i].x, mc[i].y, tag16);
        if (!any(bad & 0xffffu) || ++it > SPIN_MAX) break;
        load_mod();
      }
#pragma unroll
      for (int i = 0; i < 3; i++) {
        const float c0 = bf_hi(mc[i].x), c1 = bf_hi(mc[i].y);
        const float s0 = __uint_as_float(ms[i].x & smask), s1 = __uint_as_float(ms[i].y & smask);
        stmatrix4(sb1[i], pack_bf16(fmaf(rs[i][0], c0, s0), rs[i][1] * c0), pack_bf16(fmaf(rs[i][2], c1, s1), rs[i][3] * c1),
                  pack_bf16(rs[i][4] * c0, rs[i][5] * c0), pack_bf16(rs[i][6] * c1, rs[i][7] * c1));
      }
    }
    fence_async_smem();
    if (wg == 2) {
      bar_arrive(5, NTHR);
      if (R >= 0 && elect()) load_filter(wp - 8);
      __syncwarp();
      const int slot = 4 * (cta & 7) + ((cta >> 4) & 3) + 32 * (2 * (cta >> 6) + ((cta >> 3) & 1));
      const uint32_t c0 = upin(40 * slot), c1 = upin(60 * (wp & 1)), src = upin(sbase + O_Z1 + (wp & 1) * 9600);
      const CUtensorMap* mz = upin(&maps.z1);
      unsigned* hint = pin(sc->cnt + C_Z1 + 32 * (wp & 1));
      if (wp < 10) {
        bar_sync(2 + (wp & 1), 160);
        if (elect()) tma_st2d(mz, src, c0, c1);
        pause(HD1);
        if (elect()) red_add(hint, 1);
        bulk_commit_wait();
        __syncwarp();
      }
    } else {
      bar_sync(5, NTHR);
      float acc[36];
      const uint32_t db = (((sbase + O_B1 + wg * 9216) & 0x3FFFF) >> 4) | ((128 >> 4) << 16);
      wg_fence();
#pragma unroll
      for (int kk = 0; kk < 4; kk++) wgmma_rs_72(acc, af[kk].x, af[kk].y, af[kk].z, af[kk].w, db + kk * 16, 1024 >> 4, kk);
      wg_commit();
      wg_wait<0>();
      reg_fence(acc);
      float2 za[9], zb[9];
#pragma unroll
      for (int i = 0; i < 9; i++) { za[i] = make_float2(acc[4 * i], acc[4 * i + 2]); zb[i] = make_float2(acc[4 * i + 1], acc[4 * i + 3]); }
      dft9(za); dft9(zb);
      if ((wp & 3) == wg) {
        const float sp = g ? 0.f : 1.f;
#pragma unroll
        for (int k = 1; k < 5; k++) {
          float2 a = za[k], b = za[9 - k];
          za[k] = make_float2(fmaf(sp, b.x, a.x), fmaf(-sp, b.y, a.y)); za[9 - k] = make_float2(fmaf(-sp, a.x, b.x), fmaf(sp, a.y, b.y));
          a = zb[k]; b = zb[9 - k];
          zb[k] = make_float2(fmaf(sp, b.x, a.x), fmaf(-sp, b.y, a.y)); zb[9 - k] = make_float2(fmaf(-sp, a.x, b.x), fmaf(sp, a.y, b.y));
        }
        const uint32_t w0 = set_tag(pack_bf16(za[0].y, 0.f), tag1), w1 = pack_bf16(zb[0].y, 0.f);
        asm volatile("{\n.reg .pred p;\nsetp.eq.u32 p, %3, 0;\n@p st.shared.v2.b32 [%0], {%1,%2};\n}" ::"r"(lo[0] + 288 * 8), "r"(w0), "r"(w1), "r"(g) : "memory");
        za[0].y = g ? za[0].y : 0.f; zb[0].y = g ? zb[0].y : 0.f;
      }
#pragma unroll
      for (int k1 = 0; k1 < 9; k1++) sts2(lo[k1], set_tag(pack_bf16(za[k1].x, za[k1].y), tag1), pack_bf16(zb[k1].x, zb[k1].y));
      fence_async_smem();
      bar_arrive(2 + wg, 160);
      {
        const uint32_t fx = (((cta >> 4) ^ cta) & 3) << 3, dl = O_IN - O_Z1, st = sbase + O_ST + 15360 + tid * 16;
        sts4(st, (lo[0] ^ fx) + dl, (lo[1] ^ fx) + dl, (lo[2] ^ fx) + dl, (lo[3] ^ fx) + dl);
        sts4(st + 4096, (lo[4] ^ fx) + dl, (lo[5] ^ fx) + dl, (lo[6] ^ fx) + dl, (lo[7] ^ fx) + dl);
        sts4(st + 8192, (lo[8] ^ fx) + dl, (lo[0] ^ fx) + dl + (kap ? 0 : 288 * 8),
             sbase + O_B3 + wg * 1024 + (l >> 4) * 2048 + (2 * (kap & 24) + (l & 15)) * 16, 0);
      }
    }
    {
      uint32_t sy[6];
#pragma unroll
      for (int i = 0; i < 6; i++) {
        const int rr = 16 * (wp & 3) + g + 8 * (i & 1);
        sy[i] = sbase + O_Y + (t * 584 + 64 * ((3 * wg + (i >> 1) + 63 - rr) % 9) + rr) * 4;
      }
      sts4(sbase + O_ST + tid * 16, movm(tb[0]), movm(tb[2]), movm(tb[1]), movm(tb[3]));
      sts4(sbase + O_ST + 6144 + tid * 16, sy[0], sy[1], sy[2], sy[3]);
      sts2(sbase + O_ST + 12288 + tid * 8, sy[4], sy[5]);
    }
  } else {
    __syncthreads();
  }

  const unsigned ep = upin(lds(full0 + 248));
  const uint32_t tag16 = tag_of(ep), tag1 = ep & 1;
  auto load_wm = [&](int u) {
    if (wp > 8 && elect()) {
      mbar_expect(full0 + 8 * B_WM, 6144);
      tma2d(sbase + O_NRM + (wp - 9) * 6144, &maps.wm, 16 * u, 192 * (wp - 9), full0 + 8 * B_WM);
    }
    __syncwarp();
  };
  if (R >= 0) {
    const int nl = (col0 + wp < DF_) + (wg < 2 && col0 + wp + 12 < DF_);
    uint4 cf[2][4], G[4];
#pragma unroll
    for (int i = 0; i < 4; i++) {
      cf[0][i] = __ldg(p.tab + TB_P2 + i * 32 + l);
      cf[1][i] = __ldg(p.tab + TB_P2 + (pi ? i : 4 + i) * 32 + l);
      G[i] = __ldg(p.tab + TB_P2 + (8 + i) * 32 + l);
    }
    const uint32_t* zin = sc->z1 + (size_t)R * 5120;
    if (wp == 10) {
      const uint32_t* zu = upin(zin);
      if (elect()) mbar_expect(full0 + 8 * B_Z1, 20480);
      wait_cnt(sc->cnt + C_Z1 + 32 * (pi >> 2), 128 * ep);
      if (elect()) {
        bulk_ld(sbase + O_P2, zu, 20480, full0 + 8 * B_Z1);
      }
      __syncwarp();
    }
    mbar_wait(full0 + 8 * B_FLT, 0);
    float wn[16], wc[16];
#pragma unroll 1
    for (int ln = nl - 1; ln >= 0; ln--) {
      const int col = col0 + wp + 12 * ln, k2 = (57 * col) & 63;
      const bool cj = k2 > 32;
      const float nr = ((col & 31) == 0 && col != 0 && col != 288 ? 0.5f : 1.0f) / ((float)S_ * D_), ni = cj ? -nr : nr;
#pragma unroll
      for (int i = 0; i < 16; i++) wn[i] = wc[i];
#pragma unroll
      for (int cl = 0; cl < 2; cl++) {
        const int v = cl ^ (cj && pi), e = ((v ? xv : xu) & 15) + wp + 12 * ln, sh = e < 32 ? 6 : 5;
        const uint32_t base = sbase + O_RAW + v * 12288 + (e < 32 ? 2 * e : 8192 - 64 + 2 * e), msk = e < 32 ? 0x30 : 0x10;
        const int dm = v ? (cj || pi ? -1 : 0) : 0;
#pragma unroll
        for (int tt = 0; tt < 4; tt++) {
          const int kc = g + 64 * (tt >> 1) + 16 * t + 8 * (tt & 1);
          uint32_t a = base + ((((cj ? -kc : kc) + dm) & 127) << sh);
          a ^= (a >> 3) & msk;
          wc[4 * tt + 2 * cl] = lds_bf(a) * nr; wc[4 * tt + 2 * cl + 1] = lds_bf(a + 24576) * ni;
        }
      }
    }
    const float al = __uint_as_float(pin((pi ? 0x3f800000u : 0u) + (l >> 5)));
    const uint32_t tagv = pin(tag1 + (l >> 5));
    uint32_t off = pin(l * 160 + ((wp ^ (g & 3)) << 3));
    uint32_t offo = pin(sbase + O_P2 + 20480 + off - 64 * l), po = 3072;
    unsigned* hz2 = pin(sc->cnt + C_Z2);
    const uint32_t do2 = pin(12288 - 32 * l);
    const CUtensorMap* mz2 = upin(&maps.z2[wp == 0]);
    const uint32_t sz2 = upin(sbase + O_P2 + 20480 + (wp ? 0 : 12288)), cz2 = upin(40 * R + (wp ? 0 : 24));
    mbar_wait(full0 + 8 * B_Z1, 0);
    if (wg == 2) load_wm(72 + mu);
    uint2 v[4], v2[4];
    const uint32_t o2 = nl > 1 ? 96 : 0;
#pragma unroll
    for (int i = 0; i < 4; i++) { v[i] = lds2(sbase + O_P2 + off + i * 5120); v2[i] = lds2(sbase + O_P2 + off + o2 + i * 5120); }
    auto bad2 = [&]() {
      return any(or3(or3(diff2(v[0].x, v[1].x, tagv), diff2(v[2].x, v[3].x, tagv), diff2(v2[0].x, v2[1].x, tagv)), diff2(v2[2].x, v2[3].x, tagv), 0) & 1);
    };
    if (__builtin_expect(bad2() && nl, 0)) {
      int it = 0;
      do {
#pragma unroll
        for (int i = 0; i < 4; i++) {
          v[i] = ld_rlx2(reinterpret_cast<const uint8_t*>(zin) + off + i * 5120);
          v2[i] = ld_rlx2(reinterpret_cast<const uint8_t*>(zin) + off + o2 + i * 5120);
        }
      } while (bad2() && ++it < SPIN_MAX);
    }
#pragma unroll 1
    for (int ln = 0; ln < nl; ln++, offo += do2, po = 2048) {
      float d[4][4];
      uint32_t A[8];
#pragma unroll
      for (int h = 0; h < 2; h++) {
        mma16<false>(d[2 * h], cf[0][0].x, cf[0][0].y, cf[0][0].z, cf[0][0].w, v[h].x, v[2 + h].x);
        mma16<false>(d[2 * h + 1], cf[1][0].x, cf[1][0].y, cf[1][0].z, cf[1][0].w, v[h].y, v[2 + h].y);
      }
      if (ln) { fence_async_smem(); bar_arrive(15, NTHR); }
#pragma unroll
      for (int h = 0; h < 2; h++)
#pragma unroll
        for (int L = 0; L < 2; L++) {
          const uint4 tw = cf[L][2 + h];
          const float* z = d[2 * h + L];
          const float2 z0 = cmul(make_float2(z[0], z[2]), make_float2(__uint_as_float(tw.x), __uint_as_float(tw.y)));
          const float2 z1 = cmul(make_float2(z[1], z[3]), make_float2(__uint_as_float(tw.z), __uint_as_float(tw.w)));
          A[4 * h + L] = pack_bf16(z0.x, z0.y); A[4 * h + 2 + L] = pack_bf16(z1.x, z1.y);
        }
#pragma unroll
      for (int tt = 0; tt < 4; tt++) {
        mma16<false>(d[tt], A[0], A[1], A[2], A[3], G[tt].x, G[tt].y);
        mma16<true>(d[tt], A[4], A[5], A[6], A[7], G[tt].z, G[tt].w);
      }
#pragma unroll
      for (int tt = 0; tt < 4; tt++) {
        const float ar = d[tt][0], aj = d[tt][1], br = d[tt][2], bj = d[tt][3];
        const float2 y1 = cmul(make_float2(fmaf(-al, bj, ar), fmaf(al, br, aj)), make_float2(wc[4 * tt], wc[4 * tt + 1]));
        const float2 y2 = cmul(make_float2(fmaf(al, ar, bj), fmaf(al, aj, -br)), make_float2(wc[4 * tt + 2], wc[4 * tt + 3]));
        A[2 * tt] = pack_bf16(fmaf(al, y2.x, y1.x), fmaf(-al, y2.y, -y1.y));
        A[2 * tt + 1] = pack_bf16(fmaf(al, y1.y, -y2.y), fmaf(al, y1.x, -y2.x));
      }
#pragma unroll
      for (int i = 0; i < 16; i++) wc[i] = wn[i];
#pragma unroll
      for (int i = 0; i < 4; i++) v[i] = v2[i];
#pragma unroll
      for (int tt = 0; tt < 4; tt++) {
        mma16<false>(d[tt], A[0], A[1], A[2], A[3], G[tt].x, G[tt].y);
        mma16<true>(d[tt], A[4], A[5], A[6], A[7], G[tt].z, G[tt].w);
      }
#pragma unroll
      for (int h = 0; h < 2; h++)
#pragma unroll
        for (int L = 0; L < 2; L++) {
          const uint4 tw = cf[L][2 + h];
          const float2 z0 = cmul(make_float2(d[2 * h][2 * L], d[2 * h][2 * L + 1]), make_float2(__uint_as_float(tw.x), __uint_as_float(tw.y)));
          const float2 z1 = cmul(make_float2(d[2 * h + 1][2 * L], d[2 * h + 1][2 * L + 1]), make_float2(__uint_as_float(tw.z), __uint_as_float(tw.w)));
          A[4 * h + 2 * L] = movm(pack_bf16(z0.x, z1.x)); A[4 * h + 2 * L + 1] = movm(pack_bf16(z0.y, z1.y));
        }
#pragma unroll
      for (int h = 0; h < 2; h++) {
        mma16<false>(d[0], cf[0][1].x, cf[0][1].y, cf[0][1].z, cf[0][1].w, A[4 * h], A[4 * h + 1]);
        mma16<false>(d[1], cf[1][1].x, cf[1][1].y, cf[1][1].z, cf[1][1].w, A[4 * h + 2], A[4 * h + 3]);
#pragma unroll
        for (int e = 0; e < 2; e++)
          sts2(offo + (2 * h + e) * po, set_tag(pack_bf16(d[0][e], d[0][2 + e]), tagv), pack_bf16(d[1][e], d[1][2 + e]));
      }
    }
    fence_async_smem();
    if (nl < 2 && wp != 8) bar_arrive(15, NTHR);
    if (wp) bar_arrive(6, NTHR);
    if (!(wp & 7)) {
      bar_sync(wp ? 15 : 6, NTHR);
      if (elect()) tma_st2d(mz2, sz2, cz2, 0);
      if (wp == 0 && elect()) red_add(hz2, 1);
      if (wp == 0) bulk_commit_wait();
      __syncwarp();
    }
  }
  if (wg == 2) {
#pragma unroll 1
    for (int u = 72 + mu, k = 0; u < 216; u += NCTA, k ^= 1) {
      if (R < 0) { fence_async_smem(); bar_sync(4, 128); load_wm(u); }
      mod_unit(sc, u, t128, sbase + O_NRM, full0 + 8 * B_WM, k, red + 256 - 256 * k, tag16);
    }
    fence_async_smem();
  }

  const int grp = bx / 11, m1 = bx - 11 * grp;
  const bool helper = (m1 & 3) == 3;
  const int f1 = 384 * grp + (helper ? 192 : 128) * (m1 >> 2);
  const int d1 = 160 * (m1 & 3), flip = m1 >= 7;
  const int a1bytes = helper ? 24576 : 16384;
  auto load_a1 = [&](int st, int kb) {
    mbar_expect(full0 + 8 * st, a1bytes);
    tma4d_ef(sbase + st * STAGE, helper ? &maps.w1b : &maps.w1a, 4 * (kb >> 3), 16 * (kb & 7), f1 >> 6, full0 + 8 * st);
  };

  uint32_t bia[4];
  if (wg < 2) {
    const int fa = f1 + (helper ? 128 : 64) * (wg ^ flip) + 16 * (wp & 3) + g, fb = helper ? f1 + 64 + 16 * (wp & 3) + g : fa;
#pragma unroll
    for (int i = 0; i < 4; i++) asm volatile("ld.global.nc.u16 %0, [%1];" : "=r"(bia[i]) : "l"(p.b1 + (i < 2 ? fa : fb) + 8 * (i & 1)) : "memory");
  }
  if (rows) {
#pragma unroll
    for (int kk = 0; kk < 4; kk++) af[kk] = __ldg(p.tab + TB_E + kk * 128 + t128);
    const uint4 c0 = lds4(sbase + O_ST + tid * 16), c1 = lds4(sbase + O_ST + 6144 + tid * 16);
    const uint2 c2 = lds2(sbase + O_ST + 12288 + tid * 8);
    const uint32_t tc[4] = {c0.x, c0.y, c0.z, c0.w}, sy[6] = {c1.x, c1.y, c1.z, c1.w, c2.x, c2.y};
    const uint32_t l8 = pin(8 * l), syl = pin(sbase + O_Y + wp * 2336 + 8 * l);
    uint32_t sh3[3], ham[3];
#pragma unroll
    for (int k = 0; k < 3; k++) {
      const int pos = k && (l >> 4) == k - 1 ? 2 * (l & 6) + ((l >> 2) & 2) + (l & 1) : l & 15;
      const int sw = 2 * cta + ((wp >> 1) & 1), ph = pos ^ ((sw & 3) << 2);
      sh3[k] = pin((l >> 4) * 256 + (wp & 3) * 64 + ph * 4);
      ham[k] = pin(((ph ^ sw) & 7) == 0 ? ~1u : ~0u);
    }
    unsigned* const hh3 = upin(sc->cnt + C_H3 + (cta >> 4));
    uint8_t* const h3g = pin(sc->h3 + (cta >> 4) * (18 * 4096) + (cta & 15) * 256 + (l >> 4) * 3840);
    const int slot = 4 * (cta >> 4) + ((cta >> 1) & 3) + 32 * (2 * ((cta >> 3) & 1) + (cta & 1));
    const uint32_t* zin = sc->z2 + (size_t)slot * 4800;
    if (wg == 2) {
      {
        uint4 v[4];
        const int i3 = min(t128 + 384, 431);
        int it = 0;
        while (true) {
          uint32_t bad = 0;
#pragma unroll
          for (int k = 0; k < 4; k++) v[k] = ld_rlx4(sc->mod + 4 * (k < 3 ? t128 + 128 * k : i3));
#pragma unroll
          for (int k = 0; k < 4; k++) {
            v[k].x ^= tag16; v[k].y ^= tag16; v[k].z ^= tag16; v[k].w ^= tag16;
            bad |= v[k].x | v[k].y | v[k].z | v[k].w;
          }
          if (!any(bad & 0xffffu) || ++it > SPIN_MAX) break;
        }
#pragma unroll
        for (int k = 0; k < 4; k++) sts4(sbase + O_MOD + 16 * (k < 3 ? t128 + 128 * k : i3), v[k].x, v[k].y, v[k].z, v[k].w);
      }
      bulk_commit_wait();
      bar_sync(10, NTHR);
      mbar_wait(full0 + 8 * B_Z2, 0);
      if (elect()) {
        load_a1(wp - 8, wp - 8);
      }
      __syncwarp();
    } else {
      const uint4 e0 = lds4(sbase + O_ST + 15360 + tid * 16), e1 = lds4(sbase + O_ST + 19456 + tid * 16), e2 = lds4(sbase + O_ST + 23552 + tid * 16);
      const uint32_t li[9] = {e0.x, e0.y, e0.z, e0.w, e1.x, e1.y, e1.z, e1.w, e2.x}, lx = e2.y, sb3 = e2.z;
      bar_arrive(10, NTHR);
      if (wp == 1) {
        const uint32_t* zu = upin(zin);
        if (elect()) mbar_expect(full0 + 8 * B_Z2, 19200);
        wait_cnt(sc->cnt + C_Z2, 120 * ep);
        if (elect()) {
          bulk_ld(sbase + O_IN, zu, 19200, full0 + 8 * B_Z2);
        }
        __syncwarp();
      }
      mbar_wait(full0 + 8 * B_Z2, 0);
      uint2 v[10];
#pragma unroll
      for (int k1 = 0; k1 < 10; k1++) v[k1] = lds2(k1 < 9 ? li[k1] : lx);
      float2 za[9], zb[9];
      int it = 0;
#pragma unroll 1
      while (true) {
      const uint32_t bad = or3(or3(diff2(v[0].x, v[1].x, tag1), diff2(v[2].x, v[3].x, tag1), diff2(v[4].x, v[5].x, tag1)), diff2(v[6].x, v[7].x, tag1), diff2(v[8].x, v[9].x, tag1));
#pragma unroll
      for (int i = 0; i < 9; i++) { za[i] = make_float2(bf_lo(v[i].x), bf_hi(v[i].x)); zb[i] = make_float2(bf_lo(v[i].y), bf_hi(v[i].y)); }
      if ((wp & 3) == wg) {
        const float sp = g ? 0.f : 1.f;
#pragma unroll
        for (int k = 1; k < 5; k++) {
          float2 a = za[k], b = za[9 - k];
          za[k] = make_float2(fmaf(-sp, b.x, a.x), fmaf(sp, b.y, a.y)); za[9 - k] = make_float2(fmaf(sp, a.x, b.x), fmaf(-sp, a.y, b.y));
          a = zb[k]; b = zb[9 - k];
          zb[k] = make_float2(fmaf(-sp, b.x, a.x), fmaf(sp, b.y, a.y)); zb[9 - k] = make_float2(fmaf(sp, a.x, b.x), fmaf(-sp, a.y, b.y));
        }
        za[0].y = g ? za[0].y : bf_lo(v[9].x); zb[0].y = g ? zb[0].y : bf_lo(v[9].y);
      }
      dft9(za); dft9(zb);
#pragma unroll
      for (int n = 0; n < 8; n += 2) {
        const int i0 = (9 - n) % 9, i1 = 8 - n;
        stmatrix4(sb3 + n * 2048, pack_bf16(za[i0].x, zb[i0].x), pack_bf16(za[i0].y, zb[i0].y), pack_bf16(za[i1].x, zb[i1].x), pack_bf16(za[i1].y, zb[i1].y));
      }
      stmatrix2(sb3 + 8 * 2048, pack_bf16(za[1].x, zb[1].x), pack_bf16(za[1].y, zb[1].y));
      if (__builtin_expect(!any(bad & 1) || ++it > SPIN_MAX, 1)) break;
#pragma unroll
      for (int k1 = 0; k1 < 10; k1++) v[k1] = ld_rlx2(reinterpret_cast<const uint8_t*>(zin) + (pin(k1 < 9 ? li[k1] : lx) - (sbase + O_IN)));
      }
      fence_async_smem();
    }
    __syncthreads();
    float acc[24];
    const uint32_t db = (((sbase + O_B3 + wg * 6144) & 0x3FFFF) >> 4) | ((128 >> 4) << 16);
    wg_fence();
#pragma unroll
    for (int kk = 0; kk < 4; kk++) wgmma_rs_48(acc, af[kk].x, af[kk].y, af[kk].z, af[kk].w, db + kk * 16, 1024 >> 4, kk);
    wg_commit();
    uint32_t ga[9];
    if (wg < 2) {
#pragma unroll
      for (int i = 0; i < 9; i++) { const uint2 v = lds2(l8 + sbase + O_MOD + 256 * i); ga[i] = __byte_perm(v.x, v.y, 0x7632); }
    }
    wg_wait<0>();
    reg_fence(acc);
#pragma unroll
    for (int i = 0; i < 3; i++) {
      const float* a = &acc[8 * i];
      const uint32_t a0 = pack_bf16(a[0], a[1]), a1 = pack_bf16(a[2], a[3]), a2 = pack_bf16(a[4], a[5]), a3 = pack_bf16(a[6], a[7]);
#pragma unroll
      for (int jh = 0; jh < 2; jh++) {
        float y[4];
        mma16<false>(y, a0, a1, a2, a3, tc[2 * jh], tc[2 * jh + 1]);
        sts(sy[2 * i] + jh * (4 * 584 * 4), pack_bf16(y[0], y[1]));
        sts(sy[2 * i + 1] + jh * (4 * 584 * 4), pack_bf16(y[2], y[3]));
      }
    }
    if (wg == 2) bar_arrive(7, NTHR); else bar_sync(7, NTHR);
    if (wg) bar_sync(15, NTHR);
    if (wg < 2) {
      uint2 y[9], sh[9], sw[9];
#pragma unroll
      for (int i = 0; i < 9; i++) y[i] = lds2(syl + 256 * i);
      uint32_t sel = 0x5410, sto = sbase + O_B3 + wg * 9216;
#pragma unroll 1
      for (int e = 0; e < 2; e++, sel = 0x7632, sto += 4608) {
        float a[18];
#pragma unroll
        for (int i = 0; i < 9; i++) {
          const uint32_t x1 = hfma2(ga[i], __byte_perm(y[i].x, y[i].y, sel), xr[i]);
          xr[i] = xr[9 + i]; xr[9 + i] = x1;
          a[2 * i] = bf_lo(x1); a[2 * i + 1] = bf_hi(x1);
        }
#pragma unroll
        for (int i = 0; i < 9; i++) { lds2_if(!e, sh[i], l8 + sbase + O_MOD + 4 * D_ + 256 * i); lds2_if(!e, sw[i], l8 + sbase + O_MOD + 8 * D_ + 256 * i); }
        float oa, ra;
        ln_stats1(a, 1.0f, oa, ra);
#pragma unroll
        for (int i = 0; i < 9; i++) {
          a[2 * i] = fmaf(fmaf(a[2 * i], ra, oa), __uint_as_float(sw[i].x), __uint_as_float(sh[i].x));
          a[2 * i + 1] = fmaf(fmaf(a[2 * i + 1], ra, oa), __uint_as_float(sw[i].y), __uint_as_float(sh[i].y));
        }
        ln_stats1(a, 0.5f, oa, ra);
        uint32_t hv[9];
#pragma unroll
        for (int i = 0; i < 9; i++) hv[i] = bitsel(pack_bf16(fmaf(a[2 * i], ra, oa), fmaf(a[2 * i + 1], ra, oa)), ham[i == 2 ? 1 : i == 6 ? 2 : 0], tag1);
        if (!(wg | e)) {
          if (elect()) red_add(hh3, 1);
#pragma unroll
          for (int i = 0; i < 9; i++) asm volatile("st.global.b32 [%0], %1;" ::"l"(h3g + sh3[i == 2 ? 1 : i == 6 ? 2 : 0] + i * 8192), "r"(hv[i]) : "memory");
          bar_arrive(15, NTHR);
        } else {
#pragma unroll
          for (int i = 0; i < 9; i++) sts(sto + sh3[i == 2 ? 1 : i == 6 ? 2 : 0] + i * 512, hv[i]);
        }
        if (!e) bar_arrive(8, 288);
      }
      fence_async_smem();
      bar_arrive(9, 288);
    }
  }

  const bool g2 = rows;
  const int z2 = cta, r = z2 >> 6;
  const int s2 = 128 * ((z2 >> 2) & 15), d2 = 144 * (z2 & 3);
  constexpr int ST0 = 32 % NST;
  const bool first = helper || m1 < W0N;

  if (wg == 2) {
    asm volatile("setmaxnreg.dec.sync.aligned.u32 40;");
    const int l = lane_id(), g = l >> 2;
    auto load_b = [&](bool second, int i, int st) {
      const uint32_t lb = full0 + 8 * (B_LAND + st), bytes = second ? 18432 : STAGE - a1bytes;
      mbar_expect(lb, bytes);
      bulk_ld(sbase + (second ? st * STAGE2 + 16384 : st * STAGE + a1bytes),
              second ? sc->u + ((size_t)(36 * r + kb2_order(i)) * D_ + d2) * 128 : sc->h3 + ((size_t)(i * 18 + (d1 >> 5)) << 12), bytes, lb);
    };
    if (wp == 8) {
      int st = rows ? 4 : 0, ph = 1;
#pragma unroll 1
      for (int kb = st; kb < 32; kb++) {
        if (rows && (kb >> 1) == 2) mbar_wait(full0 + 8 * (B_S4 - 4 + kb), 0);
        mbar_wait(empty0 + 8 * st, ph);
        if (elect()) {
          load_a1(st, kb);
        }
        __syncwarp();
        ring_next<false>(st, ph);
      }
      if (g2) {
        st++;
#pragma unroll 1
        for (int i = 0; i < 36; i++) {
          if (i == HOLDA) mbar_wait(full0 + 8 * B_GO, 0);
          mbar_wait(empty0 + 8 * st, ph);
          if (elect()) {
            mbar_expect(full0 + 8 * st, 16384);
            tma3d_ef(sbase + st * STAGE2, &maps.w2, 64 * (36 * r + kb2_order(i)), s2 >> 6, full0 + 8 * st);
          }
          __syncwarp();
          ring_next<true>(st, ph);
        }
      }
    } else if (wp >= 10) {
      const int sw = wp - 10;
      if (sw) {
        if (rows) {
          bar_sync(8, 288);
          mbar_wait(full0, 0);
          if (elect()) mbar_arrive(full0 + 8 * B_S4);
          bar_sync(9, 288);
          if (elect()) tma_st3d(&maps.h3, sbase + O_B3 + 4608, 64 * (cta & 15), 18 * (cta >> 4), 1);
          bulk_commit_wait();
          if (elect()) {
            red_add(sc->cnt + C_H3 + (cta >> 4) + 8, 4);
            mbar_arrive(full0 + 8 * B_S5);
            asm volatile("fence.acq_rel.gpu;" ::: "memory");
            red_add(&sc->cnt[C_X + 64], 1);
          }
          __syncwarp();
        }
        if (g2) {
          sts(sbase + O_GB + 288 + 4 * l, ld_nc(p.b2 + s2 + 64 * (r ^ 1) + 2 * l));
          uint2 v[3];
          int it = 0;
          do {
#pragma unroll
            for (int i = 0; i < 3; i++) v[i] = ld_rlx2(sc->mod + 3 * D_ + d2 + 2 * min(l + 32 * i, 71));
          } while (any(or3(diff2(v[0].x, v[0].y, tag16), diff2(v[1].x, v[1].y, tag16), diff2(v[2].x, v[2].y, tag16)) & 0xffffu) && ++it < SPIN_MAX);
#pragma unroll
          for (int i = 0; i < 3; i++) sts(sbase + O_GB + 4 * min(l + 32 * i, 71), __byte_perm(v[i].x, v[i].y, 0x7632));
          __syncwarp();
        }
        wait_cnt<true>(&sc->cnt[C_X + 64], 128 * ep);
        if (elect()) mbar_arrive(full0 + 8 * B_X);
        __syncwarp();
      }
      uint32_t lph = 0;
      auto check_tiles = [&](bool second, int n, int st, uint32_t o1, uint32_t d2nd) {
        const uint32_t b1 = pin(sbase + o1), b2 = pin(sbase + o1 + d2nd);
        int i = 0, it = 0;
#pragma unroll 1
        do {
          const uint32_t so = st * (second ? STAGE2 : STAGE);
          mbar_wait(full0 + 8 * (B_LAND + st), (lph >> st) & 1);
          lph ^= 1u << st;
          uint32_t v[20];
#pragma unroll
          for (int k = 0; k < 20; k++) if (!second || k < 10 || k >= 12) v[k] = lds(k < 12 ? b1 + so + k * 1024 : b2 + so + (k - 12) * 1024); else v[k] = tag1;
#pragma unroll
          for (int k = 0; k < 10; k++) v[k] = diff2(v[2 * k], v[2 * k + 1], tag1);
          const uint32_t bad = or3(or3(or3(v[0], v[1], v[2]), or3(v[3], v[4], v[5]), v[6]), v[7], or3(v[8], v[9], 0));
          if (__builtin_expect(any(bad & 1) && ++it < SPIN_MAX, 0)) {
            fence_async_smem();
            __syncwarp();
            if (elect()) load_b(second, i, st);
            __syncwarp();
            continue;
          }
          if (elect()) mbar_arrive(full0 + 8 * st);
          if (++st == NST) st = 0;
          i++;
        } while (i < n);
      };
      if (!sw) check_tiles(false, NV1, 0, a1bytes + l * 32 + (l >> 2) * 4, helper ? 4096 : 12288);
      if (sw) {
#pragma unroll 1
        for (int k = 0; k < 2; k++) {
          bar_sync(13 + k, 160);
          if (helper || (first && !k)) continue;
          const uint32_t stg = sbase + (k ? O_U1 : ST0 * STAGE);
          const int kb = (f1 >> 6) + (k ^ flip);
          uint8_t* const ug = sc->u + ((size_t)kb * D_ + d1) * 128;
          if (g2) mbar_wait(full0 + 8 * B_GO, 0);
          if (first) pause(10 * TRK0);
#pragma unroll 1
          for (int i = 0; i < 20480; i += 2048) {
            if (elect()) bulk_st(ug + i, stg + i, 2048);
            pause(k ? TRKC : TRK0);
          }
          if (elect()) red_add(sc->cnt + C_U + kb2_pos(kb), 4);
          bulk_commit_wait();
          if (elect()) { if (!k) mbar_arrive(empty0 + 8 * ST0); }
          __syncwarp();
        }
        if (elect()) { asm volatile("fence.acq_rel.gpu;" ::: "memory"); red_add(&sc->cnt[C_X], 1); }
        __syncwarp();
      }
      if (g2) {
        if (!sw) check_tiles(true, NV2, 3, 16384 + l * 32 + g * 4, 10240);
        else {
          wait_cnt<true>(&sc->cnt[C_X], NCTA * ep);
          if (elect()) mbar_arrive(full0 + 8 * B_X);
          if (cta == 0) sc->cnt[C_EP + l] = ep;
          __syncwarp();
        }
      }
      __syncwarp();
    } else {
      uint32_t ready = 0;
      int st = 0, ph = 1;
#pragma unroll 1
      for (int kb = 0; kb < 32; kb++) {
        const uint8_t* src = upin(sc->h3 + ((size_t)(kb * 18 + (d1 >> 5)) << 12));
        const uint32_t dst = upin(sbase + st * STAGE + a1bytes), lb = full0 + 8 * ((kb < NV1 ? B_LAND : 0) + st);
        if (kb == NV1) { mbar_wait(full0 + 8 * B_X, 0); fence_async_glb(); ready = ~0u; }
        if (rows && (kb >> 1) == 2) mbar_wait(full0 + 8 * (B_S4 - 4 + kb), 0);
        mbar_wait(empty0 + 8 * st, ph);
        if (elect()) mbar_expect(lb, STAGE - a1bytes);
        wait_flags(sc->cnt + C_H3 + l, (kb & 7) + (kb < 8 ? 0 : 8), 64 * ep, ready);
        if (elect()) bulk_ld(dst, src, STAGE - a1bytes, lb);
        ring_next<false>(st, ph);
      }
      if (g2) {
        ready = 0;
        st++;
#pragma unroll 1
        for (int i = 0; i < 36; i++) {
          const int kb = kb2_order(i);
          const uint8_t* src = upin(sc->u + ((size_t)(36 * r + kb) * D_ + d2) * 128);
          const uint32_t dst = upin(sbase + st * STAGE2 + 16384), lb = full0 + 8 * ((i < NV2 ? B_LAND : 0) + st);
          if (i == NV2) { mbar_wait(full0 + 8 * B_X, 1); fence_async_glb(); ready = ~0u; }
          mbar_wait(empty0 + 8 * st, ph);
          if (elect()) mbar_expect(lb, 18432);
          wait_flags(sc->cnt + C_U + 64 * r + l, i & 31, 16 * ep, ready);
          if (elect()) {
            bulk_ld(dst, src, 18432, lb);
            if (i == 0) mbar_arrive(full0 + 8 * B_GO);
          }
          ring_next<true>(st, ph);
        }
      }
    }
  } else {
    asm volatile("setmaxnreg.inc.sync.aligned.u32 232;");
    const int wgu = wg;
    constexpr uint32_t sb4 = sbase >> 4;
    const int w = wp & 3;
    Ring rg = {0, 0};
    uint32_t* const x1p = p.out + (size_t)(cta + 128 * ((wp & 3) + 8 * wg)) * 288 + l;
    const int direct = helper || (first && !wg), kbA = (f1 >> 6) + (helper ? 2 : 1) * (wg ^ flip), kbB = (f1 >> 6) + 1;
    const uint32_t uo = (t >> 1) * 2048 + (16 * w + g) * 32 + (((t ^ (g >> 2)) & 1) << 4);
    const uint32_t ad = pin(sbase + (wg ? O_U1 : ST0 * STAGE) + uo);
    uint8_t* const ug0 = pin(sc->u + ((size_t)kbA * D_ + d1) * 128 + uo);
    const int ud1 = upin(helper ? (kbB - kbA) * (D_ * 128) - 3 * 4096 : 0);
    unsigned* const uh = pin(sc->cnt + C_U + kb2_pos(l ? kbB : kbA));
    const int eh = direct && !helper && !l;
    const bool utg = ((t ^ (g >> 2) ^ w) & 1) == 0;
    const uint32_t um0 = pin(utg && g < 4 ? ~1u : ~0u), um1 = pin(utg && g >= 4 ? ~1u : ~0u);
    float acc[96];
    constexpr uint32_t LA = (8192 >> 4) << 16, LB = (4096 >> 4) << 16;
    {
      const float a0 = 0.5f * bf_lo(pin(bia[0])), a1 = 0.5f * bf_lo(pin(bia[1])), b0 = 0.5f * bf_lo(pin(bia[2])), b1 = 0.5f * bf_lo(pin(bia[3]));
#pragma unroll
      for (int i = 0; i < 96; i++) acc[i] = i < 48 ? ((i & 2) ? a1 : a0) : ((i & 2) ? b1 : b0);
      reg_fence(acc);
    }
    if (!helper) gemm_main<0>(acc, sb4 + (wgu ^ flip) * 512 + LA, 0, sb4 + 1024 + LB, wgu, rg, rows, first ? NST : NST - 1, x1p, xr);
    else {
      float ac2[96];
#pragma unroll
      for (int i = 0; i < 96; i++) asm volatile("mov.b32 %0, %1;" : "=f"(ac2[i]) : "f"(acc[i]));
      gemm_main<1>(ac2, sb4 + (wgu ^ flip) * 1024 + LA, sb4 + 512 + LA, sb4 + 1536 + LB, wgu, rg, rows, NST - 1, x1p, xr);
#pragma unroll
      for (int i = 0; i < 96; i++) asm volatile("mov.b32 %0, %1;" : "=f"(acc[i]) : "f"(ac2[i]));
    }
    {
      float tp[2] = {0.f, 0.f};
#pragma unroll
      for (int j = 0; j < 12; j++) {
        const float* a = &acc[16 * (j >> 1) + 2 * (j & 1)];
        const float k3 = j < 2 ? GK3 : fmaf(tp[j & 1], 0.0f, GK3);
        uint32_t o[4];
#pragma unroll
        for (int e = 0; e < 4; e++) {
          const float h0 = a[4 * e], h1 = a[4 * e + 1];
          float z0 = h0 * fmaf(h0 * k3, h0, GK1), z1 = h1 * fmaf(h1 * k3, h1, GK1);
          asm("tanh.approx.f32 %0, %0;" : "+f"(z0));
          asm("tanh.approx.f32 %0, %0;" : "+f"(z1));
          if (e == 3) tp[j & 1] = z0;
          o[e] = pack_bf16(fmaf(h0, z0, h0), fmaf(h1, z1, h1));
          if ((e >> 1) == (j & 1)) o[e] = bitsel(o[e], (e & 1) ? um1 : um0, tag1);
        }
        if (j == EH) asm volatile("{\n.reg .pred p;\nsetp.ne.u32 p, %1, 0;\n@p red.relaxed.gpu.global.add.u32 [%0], 1;\n}" ::"l"(uh), "r"(eh) : "memory");
        asm volatile("{\n.reg .pred p;\nsetp.ne.u32 p, %6, 0;\n@p st.global.v4.b32 [%0], {%2,%3,%4,%5};\n@!p st.shared.v4.b32 [%1], {%2,%3,%4,%5};\n}"
                     ::"l"(ug0 + (j < 6 ? 0 : ud1) + (j >> 1) * 4096 + (j & 1) * 256), "r"(ad + (j >> 1) * 4096 + (j & 1) * 256),
                       "r"(o[0]), "r"(o[1]), "r"(o[2]), "r"(o[3]), "r"(direct) : "memory");
        if ((j == 5 && helper && !wgu) || (j == 9 && !helper)) break;
      }
      if (!direct) fence_async_smem();
      else if (l <= wgu && helper) red_add(uh, 1);
      __syncwarp();
      bar_arrive(13 + wgu, 160);
    }
    if (g2) {
      const int mb = wgu ^ r;
      const int odd = z2 & 1;
      uint4 gq[4];
      uint2 gs;
      {
        float a0 = 0.f, a1 = 0.f;
        if (wgu) { a0 = lds_bf(sbase + O_GB + 288 + 2 * (16 * w + g)); a1 = lds_bf(sbase + O_GB + 288 + 16 + 2 * (16 * w + g)); }
#pragma unroll
        for (int i = 0; i < 4; i++) gq[i] = lds4(sbase + O_GB + 32 * odd + 64 * i + 16 * t);
        gs = lds2(sbase + O_GB + (odd ? 0 : 256) + 8 * t);
#pragma unroll
        for (int i = 0; i < 72; i++) acc[i] = (i & 2) ? a1 : a0;
      }
      uint32_t* const ob = p.out + (size_t)(s2 + 64 * mb + 16 * w + g) * 288 + (d2 >> 1);
      uint32_t* const oq = pin(ob + 8 * odd + 4 * t);
      uint32_t* const os = pin(ob + (odd ? 0 : 64) + 2 * t);
      rg.st++;
      gemm_main<3>(acc, sb4 + mb * 512 + LA, 0, sb4 + 1024 + ((2048 >> 4) << 16), wgu, rg, rows, NST, x1p, xr);
      auto finish = [&](const float* aq, const float* as) {
#pragma unroll
        for (int i = 0; i < 8; i++) {
          const float* a = aq + 16 * (i >> 1) + 2 * (i & 1);
          const uint4 gv = gq[i >> 1];
          red_bf16x8(oq + (i & 1) * 2304 + 16 * (i >> 1), hmul2(gv.x, pack_bf16(a[0], a[1])), hmul2(gv.y, pack_bf16(a[4], a[5])),
                     hmul2(gv.z, pack_bf16(a[8], a[9])), hmul2(gv.w, pack_bf16(a[12], a[13])));
        }
#pragma unroll
        for (int i = 0; i < 2; i++) red_bf16x4(os + i * 2304, hmul2(gs.x, pack_bf16(as[2 * i], as[2 * i + 1])), hmul2(gs.y, pack_bf16(as[2 * i + 4], as[2 * i + 5])));
      };
      if (odd) finish(&acc[8], &acc[0]); else finish(&acc[0], &acc[64]);
      __syncwarp();
    }
  }
}

typedef CUresult (*EncodeFn)(CUtensorMap*, CUtensorMapDataType, cuuint32_t, void*, const cuuint64_t*, const cuuint64_t*, const cuuint32_t*,
                             const cuuint32_t*, CUtensorMapInterleave, CUtensorMapSwizzle, CUtensorMapL2promotion, CUtensorMapFloatOOBfill);

struct Dim { cuuint64_t n, stride; cuuint32_t box; };
template <int RANK>
void make_map(EncodeFn enc, CUtensorMap* m, bool words, int swz, const void* ptr, const Dim (&d)[RANK]) {
  cuuint64_t gd[RANK], gs[RANK];
  cuuint32_t bx[RANK], es[RANK];
  for (int i = 0; i < RANK; i++) { gd[i] = d[i].n; gs[i] = d[i].stride; bx[i] = d[i].box; es[i] = 1; }
  enc(m, words ? CU_TENSOR_MAP_DATA_TYPE_UINT32 : CU_TENSOR_MAP_DATA_TYPE_BFLOAT16, RANK, const_cast<void*>(ptr), gd, gs + 1, bx, es,
      CU_TENSOR_MAP_INTERLEAVE_NONE, static_cast<CUtensorMapSwizzle>(swz),
      swz == 3 ? CU_TENSOR_MAP_L2_PROMOTION_L2_256B : CU_TENSOR_MAP_L2_PROMOTION_NONE, CU_TENSOR_MAP_FLOAT_OOB_FILL_NONE);
}

}

extern "C" void kernel_launch(void* const* d_in, const int* in_sizes, int n_in, void* d_out, int out_size) {
  (void)in_sizes; (void)n_in; (void)out_size;
  static EncodeFn enc = nullptr;
  static void *sptr = nullptr, *tptr = nullptr;
  if (!enc) {
    void* f = nullptr; cudaDriverEntryPointQueryResult qr;
    cudaGetDriverEntryPoint("cuTensorMapEncodeTiled", &f, cudaEnableDefault, &qr);
    enc = reinterpret_cast<EncodeFn>(f);
    cudaFuncSetAttribute(fused_kernel, cudaFuncAttributeMaxDynamicSharedMemorySize, SMEM_BYTES);
    cudaGetSymbolAddress(&sptr, g_s);
    cudaGetSymbolAddress(&tptr, T_TAB);
  }
  Params p;
  p.x = (const __nv_bfloat16*)d_in[0]; p.wr = (const __nv_bfloat16*)d_in[1]; p.wi = (const __nv_bfloat16*)d_in[2];
  p.b1 = (const __nv_bfloat16*)d_in[5]; p.b2 = (const __nv_bfloat16*)d_in[7];
  p.c = (const __nv_bfloat16*)d_in[8]; p.wmod = (const __nv_bfloat16*)d_in[9];
  p.w1 = (const __nv_bfloat16*)d_in[4]; p.w2 = (const __nv_bfloat16*)d_in[6];
  p.out = static_cast<uint32_t*>(d_out); p.s = static_cast<Scratch*>(sptr); p.tab = static_cast<const uint4*>(tptr);
  Maps maps;
  make_map<4>(enc, &maps.w1a, false, 3, p.w1, {{64, 0, 64}, {16, 128 * 2 * F_, 4}, {128, 2 * F_, 16}, {72, 128, 2}});
  make_map<4>(enc, &maps.w1b, false, 3, p.w1, {{64, 0, 64}, {16, 128 * 2 * F_, 4}, {128, 2 * F_, 16}, {72, 128, 3}});
  make_map<3>(enc, &maps.w2, false, 3, p.w2, {{64, 0, 64}, {F_, 2 * S_, 64}, {32, 128, 2}});
  make_map<2>(enc, &maps.z1, true, 0, p.s->z1, {{5120, 0, 40}, {120, 20480, 60}});
  for (int i = 0; i < 2; i++) make_map<2>(enc, &maps.z2[i], true, 0, p.s->z2, {{4800, 0, i ? 16u : 24u}, {128, 19200, 128}});
  for (int i = 0; i < 4; i++) make_map<2>(enc, &maps.wf[i], false, 2 - (i & 1), (i & 2) ? p.wi : p.wr, {{16 * DF_, 0, (i & 1) ? 16u : 32u}, {128, 32 * DF_, 128}});
  make_map<2>(enc, &maps.wm, false, 1, p.wmod, {{6 * D_, 0, 16}, {D_, 12 * D_, 192}});
  make_map<3>(enc, &maps.h3, true, 0, p.s->h3, {{1024, 0, 64}, {144, 4096, 18}, {4, 144 * 4096, 3}});
  fused_kernel<<<NCTA, NTHR, SMEM_BYTES, cudaStreamPerThread>>>(p, maps);
}
```

```cpp
#include <cuda_runtime.h>
#include <cuda_bf16.h>
#include <cuda.h>
#include <stdint.h>

namespace {

constexpr int S_ = 2048, D_ = 576, DF_ = 289, F_ = 4608;
constexpr int NCTA = 132, NTHR = 384;
constexpr int STAGE = 36864, NST = 6;
constexpr int STAGE2 = 34816, O_U1 = NST * STAGE2, O_GB = O_U1 + 20480, SMEM_BYTES = 232448;
constexpr uint32_t sbase = 1024, red = sbase + NST * STAGE, full0 = sbase + SMEM_BYTES - 256, empty0 = full0 + 8 * NST;
constexpr int O_NRM = 0, O_B1 = 19456, O_Z1 = 38912, O_P2 = 59392, O_ST = 3 * STAGE;
constexpr int O_RAW = 4 * STAGE;
constexpr int O_IN = 4 * STAGE, O_Y = O_IN + 19456, O_B3 = O_IN + 38912, O_MOD = O_IN + 57344;

__device__ __align__(128) const uint32_t T_TAB[5632] = {
0x3f803f80,0xbf803f80,0x3f803f80,0xbf803f80,0x3f803f80,0xbf803f80,0x3f803f80,0xbf803f80,0x3f803f80,0xbf803f80,0x3f803f80,0xbf803f80,
0x3f803f80,0xbf803f80,0x3f803f80,0xbf803f80,0x3f7f3f80,0xbdc90000,0x3f223f35,0xbf46bf35,0x3f753f7b,0xbe95be48,0x3ef13f0e,0xbf62bf55,
0x3f623f6d,0xbef1bec4,0x3e953ec4,0xbf75bf6d,0x3f463f55,0xbf22bf0e,0x3dc93e48,0xbf7fbf7b,0x3f7b3f80,0xbe480000,0xbe480000,0xbf7bbf80,
0x3f553f6d,0xbf0ebec4,0xbf0ebec4,0xbf55bf6d,0x3f0e3f35,0xbf55bf35,0xbf55bf35,0xbf0ebf35,0x3e483ec4,0xbf7bbf6d,0xbf7bbf6d,0xbe48bec4,
0x3f753f80,0xbe950000,0xbf62bf35,0xbef1bf35,0x3f223f55,0xbf46bf0e,0xbf7fbf7b,0x3dc9be48,0x3dc93ec4,0xbf7fbf6d,0xbf46bf6d,0x3f223ec4,
0xbef1be48,0xbf62bf7b,0xbe95bf0e,0x3f753f55,0x3f6d3f80,0xbec40000,0xbf6dbf80,0x3ec40000,0x3ec43f35,0xbf6dbf35,0xbec4bf35,0x3f6d3f35,
0xbec40000,0xbf6dbf80,0x3ec40000,0x3f6d3f80,0xbf6dbf35,0xbec4bf35,0x3f6d3f35,0x3ec43f35,0x3f623f80,0xbef10000,0xbe95bf35,0x3f753f35,
0x3dc93f0e,0xbf7fbf55,0x3f223e48,0x3f463f7b,0xbf46bec4,0xbf22bf6d,0x3f7f3f6d,0xbdc93ec4,0xbf75bf7b,0x3e95be48,0x3ef13f55,0xbf62bf0e,
0x3f553f80,0xbf0e0000,0x3f0e0000,0x3f553f80,0xbe483ec4,0xbf7bbf6d,0x3f7b3f6d,0xbe483ec4,0xbf7bbf35,0xbe48bf35,0x3e483f35,0xbf7bbf35,
0xbf0ebf6d,0x3f553ec4,0xbf55bec4,0xbf0ebf6d,0x3f463f80,0xbf220000,0x3f7f3f35,0x3dc93f35,0xbef13e48,0xbf62bf7b,0x3e953f55,0xbf75bf0e,
0xbf75bf6d,0x3e95bec4,0xbf62bec4,0xbef1bf6d,0x3dc9bf0e,0x3f7f3f55,0xbf22bf7b,0x3f463e48,0x3f353f80,0xbf350000,0x3f353f80,0xbf350000,
0xbf350000,0xbf35bf80,0xbf350000,0xbf35bf80,0xbf35bf80,0x3f350000,0xbf35bf80,0x3f350000,0x3f350000,0x3f353f80,0x3f350000,0x3f353f80,
0x3f223f80,0xbf460000,0xbdc93f35,0xbf7fbf35,0xbf62be48,0xbef1bf7b,0xbf75bf55,0x3e95bf0e,0xbe95bf6d,0x3f753ec4,0x3ef1bec4,0x3f623f6d,
0x3f7f3f0e,0x3dc93f55,0x3f463f7b,0xbf223e48,0x3f0e3f80,0xbf550000,0xbf550000,0xbf0ebf80,0xbf7bbec4,0xbe48bf6d,0xbe48bf6d,0x3f7b3ec4,
0x3e48bf35,0x3f7b3f35,0x3f7b3f35,0xbe483f35,0x3f553f6d,0xbf0e3ec4,0xbf0e3ec4,0xbf55bf6d,0x3ef13f80,0xbf620000,0xbf75bf35,0x3e95bf35,
0xbf7fbf0e,0x3dc9bf55,0x3f46be48,0x3f223f7b,0x3f22bec4,0x3f463f6d,0x3dc93f6d,0xbf7fbec4,0x3e953f7b,0xbf75be48,0xbf62bf55,0x3ef1bf0e,
0x3ec43f80,0xbf6d0000,0xbec4bf80,0x3f6d0000,0xbf6dbf35,0x3ec4bf35,0x3f6d3f35,0xbec43f35,0x3f6d0000,0x3ec43f80,0xbf6d0000,0xbec4bf80,
0xbec43f35,0xbf6dbf35,0x3ec4bf35,0x3f6d3f35,0x3e953f80,0xbf750000,0x3ef1bf35,0x3f623f35,0xbf46bf55,0x3f22bf0e,0x3dc93f7b,0xbf7fbe48,
0x3f7f3ec4,0xbdc93f6d,0xbf22bf6d,0x3f46bec4,0xbf623e48,0xbef1bf7b,0x3f753f0e,0xbe953f55,0x3e483f80,0xbf7b0000,0x3f7b0000,0x3e483f80,
0xbf0ebf6d,0x3f55bec4,0xbf553ec4,0xbf0ebf6d,0x3f553f35,0xbf0e3f35,0x3f0ebf35,0x3f553f35,0xbf7bbec4,0x3e48bf6d,0xbe483f6d,0xbf7bbec4,
0x3dc93f80,0xbf7f0000,0x3f463f35,0xbf223f35,0xbe95bf7b,0x3f75be48,0xbf62bf0e,0x3ef1bf55,0x3ef13f6d,0xbf623ec4,0x3f753ec4,0xbe953f6d,
0xbf22bf55,0x3f46bf0e,0xbf7fbe48,0x3dc9bf7b,0x3f80,0xbf800000,0x3f80,0xbf800000,0xbf80,0x3f800000,0xbf80,0x3f800000,
0x3f80,0xbf800000,0x3f80,0xbf800000,0xbf80,0x3f800000,0xbf80,0x3f800000,0xbdc93f80,0xbf7f0000,0xbf463f35,0xbf22bf35,
0x3e95bf7b,0x3f753e48,0x3f62bf0e,0x3ef13f55,0xbef13f6d,0xbf62bec4,0xbf753ec4,0xbe95bf6d,0x3f22bf55,0x3f463f0e,0x3f7fbe48,0x3dc93f7b,
0xbe483f80,0xbf7b0000,0xbf7b0000,0x3e48bf80,0x3f0ebf6d,0x3f553ec4,0x3f553ec4,0xbf0e3f6d,0xbf553f35,0xbf0ebf35,0xbf0ebf35,0x3f55bf35,
0x3f7bbec4,0x3e483f6d,0x3e483f6d,0xbf7b3ec4,0xbe953f80,0xbf750000,0xbef1bf35,0x3f62bf35,0x3f46bf55,0x3f223f0e,0xbdc93f7b,0xbf7f3e48,
0xbf7f3ec4,0xbdc9bf6d,0x3f22bf6d,0x3f463ec4,0x3f623e48,0xbef13f7b,0xbf753f0e,0xbe95bf55,0xbec43f80,0xbf6d0000,0x3ec4bf80,0x3f6d0000,
0x3f6dbf35,0x3ec43f35,0xbf6d3f35,0xbec4bf35,0xbf6d0000,0x3ec4bf80,0x3f6d0000,0xbec43f80,0x3ec43f35,0xbf6d3f35,0xbec4bf35,0x3f6dbf35,
0xbef13f80,0xbf620000,0x3f75bf35,0x3e953f35,0x3f7fbf0e,0x3dc93f55,0xbf46be48,0x3f22bf7b,0xbf22bec4,0x3f46bf6d,0xbdc93f6d,0xbf7f3ec4,
0xbe953f7b,0xbf753e48,0x3f62bf55,0x3ef13f0e,0xbf0e3f80,0xbf550000,0x3f550000,0xbf0e3f80,0x3f7bbec4,0xbe483f6d,0x3e48bf6d,0x3f7bbec4,
0xbe48bf35,0x3f7bbf35,0xbf7b3f35,0xbe48bf35,0xbf553f6d,0xbf0ebec4,0x3f0e3ec4,0xbf553f6d,0xbf223f80,0xbf460000,0x3dc93f35,0xbf7f3f35,
0x3f62be48,0xbef13f7b,0x3f75bf55,0x3e953f0e,0x3e95bf6d,0x3f75bec4,0xbef1bec4,0x3f62bf6d,0xbf7f3f0e,0x3dc9bf55,0xbf463f7b,0xbf22be48,
0xbf353f80,0xbf350000,0xbf353f80,0xbf350000,0x3f350000,0xbf353f80,0x3f350000,0xbf353f80,0x3f35bf80,0x3f350000,0x3f35bf80,0x3f350000,
0xbf350000,0x3f35bf80,0xbf350000,0x3f35bf80,0xbf463f80,0xbf220000,0xbf7f3f35,0x3dc9bf35,0x3ef13e48,0xbf623f7b,0xbe953f55,0xbf753f0e,
0x3f75bf6d,0x3e953ec4,0x3f62bec4,0xbef13f6d,0xbdc9bf0e,0x3f7fbf55,0x3f22bf7b,0x3f46be48,0xbf553f80,0xbf0e0000,0xbf0e0000,0x3f55bf80,
0x3e483ec4,0xbf7b3f6d,0xbf7b3f6d,0xbe48bec4,0x3f7bbf35,0xbe483f35,0xbe483f35,0xbf7b3f35,0x3f0ebf6d,0x3f55bec4,0x3f55bec4,0xbf0e3f6d,
0xbf623f80,0xbef10000,0x3e95bf35,0x3f75bf35,0xbdc93f0e,0xbf7f3f55,0xbf223e48,0x3f46bf7b,0x3f46bec4,0xbf223f6d,0xbf7f3f6d,0xbdc9bec4,
0x3f75bf7b,0x3e953e48,0xbef13f55,0xbf623f0e,0xbf6d3f80,0xbec40000,0x3f6dbf80,0x3ec40000,0xbec43f35,0xbf6d3f35,0x3ec4bf35,0x3f6dbf35,
0x3ec40000,0xbf6d3f80,0xbec40000,0x3f6dbf80,0x3f6dbf35,0xbec43f35,0xbf6d3f35,0x3ec4bf35,0xbf753f80,0xbe950000,0x3f62bf35,0xbef13f35,
0xbf223f55,0xbf463f0e,0x3f7fbf7b,0x3dc93e48,0xbdc93ec4,0xbf7f3f6d,0x3f46bf6d,0x3f22bec4,0x3ef1be48,0xbf623f7b,0x3e95bf0e,0x3f75bf55,
0xbf7b3f80,0xbe480000,0x3e480000,0xbf7b3f80,0xbf553f6d,0xbf0e3ec4,0x3f0ebec4,0xbf553f6d,0xbf0e3f35,0xbf553f35,0x3f55bf35,0xbf0e3f35,
0xbe483ec4,0xbf7b3f6d,0x3f7bbf6d,0xbe483ec4,0xbf7f3f80,0xbdc90000,0xbf223f35,0xbf463f35,0xbf753f7b,0xbe953e48,0xbef13f0e,0xbf623f55,
0xbf623f6d,0xbef13ec4,0xbe953ec4,0xbf753f6d,0xbf463f55,0xbf223f0e,0xbdc93e48,0xbf7f3f7b,0x3f803f80,0xbf803f80,0x3f803f80,0xbf803f80,
0x3f803f80,0xbf803f80,0x3f803f80,0xbf803f80,0x3f803f80,0xbf803f80,0x3f803f80,0xbf803f80,0x3f803f80,0xbf803f80,0x3f803f80,0xbf803f80,
0xbdc90000,0xbf7fbf80,0xbf46bf35,0xbf22bf35,0xbe95be48,0xbf75bf7b,0xbf62bf55,0xbef1bf0e,0xbef1bec4,0xbf62bf6d,0xbf75bf6d,0xbe95bec4,
0xbf22bf0e,0xbf46bf55,0xbf7fbf7b,0xbdc9be48,0xbf7bbf80,0x3e480000,0x3e480000,0x3f7b3f80,0xbf55bf6d,0x3f0e3ec4,0x3f0e3ec4,0x3f553f6d,
0xbf0ebf35,0x3f553f35,0x3f553f35,0x3f0e3f35,0xbe48bec4,0x3f7b3f6d,0x3f7b3f6d,0x3e483ec4,0x3e950000,0x3f753f80,0x3ef13f35,0xbf62bf35,
0x3f463f0e,0x3f223f55,0xbdc93e48,0xbf7fbf7b,0x3f7f3f6d,0x3dc93ec4,0xbf22bec4,0xbf46bf6d,0x3f623f7b,0xbef1be48,0xbf75bf55,0xbe95bf0e,
0x3f6d3f80,0xbec40000,0xbf6dbf80,0x3ec40000,0x3ec43f35,0xbf6dbf35,0xbec4bf35,0x3f6d3f35,0xbec40000,0xbf6dbf80,0x3ec40000,0x3f6d3f80,
0xbf6dbf35,0xbec4bf35,0x3f6d3f35,0x3ec43f35,0xbef10000,0xbf62bf80,0x3f753f35,0x3e953f35,0xbf7fbf55,0xbdc9bf0e,0x3f463f7b,0xbf22be48,
0xbf22bf6d,0x3f463ec4,0xbdc93ec4,0xbf7fbf6d,0x3e95be48,0x3f753f7b,0xbf62bf0e,0xbef1bf55,0xbf55bf80,0x3f0e0000,0xbf0e0000,0xbf55bf80,
0x3e48bec4,0x3f7b3f6d,0xbf7bbf6d,0x3e48bec4,0x3f7b3f35,0x3e483f35,0xbe48bf35,0x3f7b3f35,0x3f0e3f6d,0xbf55bec4,0x3f553ec4,0x3f0e3f6d,
0x3f220000,0x3f463f80,0xbdc9bf35,0x3f7f3f35,0x3f623f7b,0xbef13e48,0x3f753f0e,0x3e953f55,0xbe953ec4,0xbf75bf6d,0x3ef13f6d,0xbf62bec4,
0xbf7fbf55,0x3dc9bf0e,0xbf46be48,0xbf22bf7b,0x3f353f80,0xbf350000,0x3f353f80,0xbf350000,0xbf350000,0xbf35bf80,0xbf350000,0xbf35bf80,
0xbf35bf80,0x3f350000,0xbf35bf80,0x3f350000,0x3f350000,0x3f353f80,0x3f350000,0x3f353f80,0xbf460000,0xbf22bf80,0xbf7fbf35,0x3dc9bf35,
0xbef1bf7b,0x3f623e48,0x3e95bf0e,0x3f753f55,0x3f753ec4,0x3e953f6d,0x3f623f6d,0xbef13ec4,0x3dc93f55,0xbf7fbf0e,0xbf223e48,0xbf46bf7b,
0xbf0ebf80,0x3f550000,0x3f550000,0x3f0e3f80,0x3f7b3ec4,0x3e483f6d,0x3e483f6d,0xbf7bbec4,0xbe483f35,0xbf7bbf35,0xbf7bbf35,0x3e48bf35,
0xbf55bf6d,0x3f0ebec4,0x3f0ebec4,0x3f553f6d,0x3f620000,0x3ef13f80,0xbe953f35,0xbf75bf35,0xbdc93f55,0xbf7fbf0e,0xbf22bf7b,0x3f46be48,
0xbf46bf6d,0x3f22bec4,0x3f7f3ec4,0x3dc93f6d,0x3f753e48,0x3e953f7b,0xbef13f0e,0xbf62bf55,0x3ec43f80,0xbf6d0000,0xbec4bf80,0x3f6d0000,
0xbf6dbf35,0x3ec4bf35,0x3f6d3f35,0xbec43f35,0x3f6d0000,0x3ec43f80,0xbf6d0000,0xbec4bf80,0xbec43f35,0xbf6dbf35,0x3ec4bf35,0x3f6d3f35,
0xbf750000,0xbe95bf80,0x3f623f35,0xbef13f35,0x3f22bf0e,0x3f463f55,0xbf7fbe48,0xbdc9bf7b,0xbdc93f6d,0xbf7fbec4,0x3f46bec4,0x3f223f6d,
0xbef1bf7b,0x3f62be48,0xbe953f55,0xbf75bf0e,0xbe48bf80,0x3f7b0000,0xbf7b0000,0xbe48bf80,0x3f0e3f6d,0xbf553ec4,0x3f55bec4,0x3f0e3f6d,
0xbf55bf35,0x3f0ebf35,0xbf0e3f35,0xbf55bf35,0x3f7b3ec4,0xbe483f6d,0x3e48bf6d,0x3f7b3ec4,0x3f7f0000,0x3dc93f80,0x3f22bf35,0x3f463f35,
0xbf753e48,0xbe95bf7b,0xbef13f55,0xbf62bf0e,0x3f62bec4,0x3ef13f6d,0x3e95bf6d,0x3f753ec4,0xbf463f0e,0xbf22bf55,0xbdc93f7b,0xbf7fbe48,
0x3f80,0xbf800000,0x3f80,0xbf800000,0xbf80,0x3f800000,0xbf80,0x3f800000,0x3f80,0xbf800000,0x3f80,0xbf800000,
0xbf80,0x3f800000,0xbf80,0x3f800000,0xbf7f0000,0x3dc9bf80,0xbf22bf35,0x3f46bf35,0x3f753e48,0xbe953f7b,0x3ef13f55,0xbf623f0e,
0xbf62bec4,0x3ef1bf6d,0xbe95bf6d,0x3f75bec4,0x3f463f0e,0xbf223f55,0x3dc93f7b,0xbf7f3e48,0x3e48bf80,0x3f7b0000,0x3f7b0000,0xbe483f80,
0xbf0e3f6d,0xbf55bec4,0xbf55bec4,0x3f0ebf6d,0x3f55bf35,0x3f0e3f35,0x3f0e3f35,0xbf553f35,0xbf7b3ec4,0xbe48bf6d,0xbe48bf6d,0x3f7bbec4,
0x3f750000,0xbe953f80,0xbf623f35,0xbef1bf35,0xbf22bf0e,0x3f46bf55,0x3f7fbe48,0xbdc93f7b,0x3dc93f6d,0xbf7f3ec4,0xbf46bec4,0x3f22bf6d,
0x3ef1bf7b,0x3f623e48,0x3e953f55,0xbf753f0e,0xbec43f80,0xbf6d0000,0x3ec4bf80,0x3f6d0000,0x3f6dbf35,0x3ec43f35,0xbf6d3f35,0xbec4bf35,
0xbf6d0000,0x3ec4bf80,0x3f6d0000,0xbec43f80,0x3ec43f35,0xbf6d3f35,0xbec4bf35,0x3f6dbf35,0xbf620000,0x3ef1bf80,0x3e953f35,0xbf753f35,
0x3dc93f55,0xbf7f3f0e,0x3f22bf7b,0x3f463e48,0x3f46bf6d,0x3f223ec4,0xbf7f3ec4,0x3dc9bf6d,0xbf753e48,0x3e95bf7b,0x3ef13f0e,0xbf623f55,
0x3f0ebf80,0x3f550000,0xbf550000,0x3f0ebf80,0xbf7b3ec4,0x3e48bf6d,0xbe483f6d,0xbf7b3ec4,0x3e483f35,0xbf7b3f35,0x3f7bbf35,0x3e483f35,
0x3f55bf6d,0x3f0e3ec4,0xbf0ebec4,0x3f55bf6d,0x3f460000,0xbf223f80,0x3f7fbf35,0x3dc93f35,0x3ef1bf7b,0x3f62be48,0xbe95bf0e,0x3f75bf55,
0xbf753ec4,0x3e95bf6d,0xbf623f6d,0xbef1bec4,0xbdc93f55,0xbf7f3f0e,0x3f223e48,0xbf463f7b,0xbf353f80,0xbf350000,0xbf353f80,0xbf350000,
0x3f350000,0xbf353f80,0x3f350000,0xbf353f80,0x3f35bf80,0x3f350000,0x3f35bf80,0x3f350000,0xbf350000,0x3f35bf80,0xbf350000,0x3f35bf80,
0xbf220000,0x3f46bf80,0x3dc9bf35,0x3f7fbf35,0xbf623f7b,0xbef1be48,0xbf753f0e,0x3e95bf55,0x3e953ec4,0xbf753f6d,0xbef13f6d,0xbf623ec4,
0x3f7fbf55,0x3dc93f0e,0x3f46be48,0xbf223f7b,0x3f55bf80,0x3f0e0000,0x3f0e0000,0xbf553f80,0xbe48bec4,0x3f7bbf6d,0x3f7bbf6d,0x3e483ec4,
0xbf7b3f35,0x3e48bf35,0x3e48bf35,0x3f7bbf35,0xbf0e3f6d,0xbf553ec4,0xbf553ec4,0x3f0ebf6d,0x3ef10000,0xbf623f80,0xbf753f35,0x3e95bf35,
0x3f7fbf55,0xbdc93f0e,0xbf463f7b,0xbf223e48,0x3f22bf6d,0x3f46bec4,0x3dc93ec4,0xbf7f3f6d,0xbe95be48,0x3f75bf7b,0x3f62bf0e,0xbef13f55,
0xbf6d3f80,0xbec40000,0x3f6dbf80,0x3ec40000,0xbec43f35,0xbf6d3f35,0x3ec4bf35,0x3f6dbf35,0x3ec40000,0xbf6d3f80,0xbec40000,0x3f6dbf80,
0x3f6dbf35,0xbec43f35,0xbf6d3f35,0x3ec4bf35,0xbe950000,0x3f75bf80,0xbef13f35,0xbf623f35,0xbf463f0e,0x3f22bf55,0x3dc93e48,0xbf7f3f7b,
0xbf7f3f6d,0x3dc9bec4,0x3f22bec4,0xbf463f6d,0xbf623f7b,0xbef13e48,0x3f75bf55,0xbe953f0e,0x3f7bbf80,0x3e480000,0xbe480000,0x3f7bbf80,
0x3f55bf6d,0x3f0ebec4,0xbf0e3ec4,0x3f55bf6d,0x3f0ebf35,0x3f55bf35,0xbf553f35,0x3f0ebf35,0x3e48bec4,0x3f7bbf6d,0xbf7b3f6d,0x3e48bec4,
0x3dc90000,0xbf7f3f80,0x3f46bf35,0xbf223f35,0x3e95be48,0xbf753f7b,0x3f62bf55,0xbef13f0e,0x3ef1bec4,0xbf623f6d,0x3f75bf6d,0xbe953ec4,
0x3f22bf0e,0xbf463f55,0x3f7fbf7b,0xbdc93e48,0x3f803f80,0xbf803f80,0x3f803f80,0xbf803f80,0x3f803f80,0xbf803f80,0x3f803f80,0xbf803f80,
0x3f803f80,0xbf803f80,0x3f803f80,0xbf803f80,0x3f803f80,0xbf803f80,0x3f803f80,0xbf803f80,0xbf7fbf80,0x3dc90000,0xbf22bf35,0x3f463f35,
0xbf75bf7b,0x3e953e48,0xbef1bf0e,0x3f623f55,0xbf62bf6d,0x3ef13ec4,0xbe95bec4,0x3f753f6d,0xbf46bf55,0x3f223f0e,0xbdc9be48,0x3f7f3f7b,
0x3f7b3f80,0xbe480000,0xbe480000,0xbf7bbf80,0x3f553f6d,0xbf0ebec4,0xbf0ebec4,0xbf55bf6d,0x3f0e3f35,0xbf55bf35,0xbf55bf35,0xbf0ebf35,
0x3e483ec4,0xbf7bbf6d,0xbf7bbf6d,0xbe48bec4,0xbf75bf80,0x3e950000,0x3f623f35,0x3ef13f35,0xbf22bf55,0x3f463f0e,0x3f7f3f7b,0xbdc93e48,
0xbdc9bec4,0x3f7f3f6d,0x3f463f6d,0xbf22bec4,0x3ef13e48,0x3f623f7b,0x3e953f0e,0xbf75bf55,0x3f6d3f80,0xbec40000,0xbf6dbf80,0x3ec40000,
0x3ec43f35,0xbf6dbf35,0xbec4bf35,0x3f6d3f35,0xbec40000,0xbf6dbf80,0x3ec40000,0x3f6d3f80,0xbf6dbf35,0xbec4bf35,0x3f6d3f35,0x3ec43f35,
0xbf62bf80,0x3ef10000,0x3e953f35,0xbf75bf35,0xbdc9bf0e,0x3f7f3f55,0xbf22be48,0xbf46bf7b,0x3f463ec4,0x3f223f6d,0xbf7fbf6d,0x3dc9bec4,
0x3f753f7b,0xbe953e48,0xbef1bf55,0x3f623f0e,0x3f553f80,0xbf0e0000,0x3f0e0000,0x3f553f80,0xbe483ec4,0xbf7bbf6d,0x3f7b3f6d,0xbe483ec4,
0xbf7bbf35,0xbe48bf35,0x3e483f35,0xbf7bbf35,0xbf0ebf6d,0x3f553ec4,0xbf55bec4,0xbf0ebf6d,0xbf46bf80,0x3f220000,0xbf7fbf35,0xbdc9bf35,
0x3ef1be48,0x3f623f7b,0xbe95bf55,0x3f753f0e,0x3f753f6d,0xbe953ec4,0x3f623ec4,0x3ef13f6d,0xbdc93f0e,0xbf7fbf55,0x3f223f7b,0xbf46be48,
0x3f353f80,0xbf350000,0x3f353f80,0xbf350000,0xbf350000,0xbf35bf80,0xbf350000,0xbf35bf80,0xbf35bf80,0x3f350000,0xbf35bf80,0x3f350000,
0x3f350000,0x3f353f80,0x3f350000,0x3f353f80,0xbf22bf80,0x3f460000,0x3dc9bf35,0x3f7f3f35,0x3f623e48,0x3ef13f7b,0x3f753f55,0xbe953f0e,
0x3e953f6d,0xbf75bec4,0xbef13ec4,0xbf62bf6d,0xbf7fbf0e,0xbdc9bf55,0xbf46bf7b,0x3f22be48,0x3f0e3f80,0xbf550000,0xbf550000,0xbf0ebf80,
0xbf7bbec4,0xbe48bf6d,0xbe48bf6d,0x3f7b3ec4,0x3e48bf35,0x3f7b3f35,0x3f7b3f35,0xbe483f35,0x3f553f6d,0xbf0e3ec4,0xbf0e3ec4,0xbf55bf6d,
0xbef1bf80,0x3f620000,0x3f753f35,0xbe953f35,0x3f7f3f0e,0xbdc93f55,0xbf463e48,0xbf22bf7b,0xbf223ec4,0xbf46bf6d,0xbdc9bf6d,0x3f7f3ec4,
0xbe95bf7b,0x3f753e48,0x3f623f55,0xbef13f0e,0x3ec43f80,0xbf6d0000,0xbec4bf80,0x3f6d0000,0xbf6dbf35,0x3ec4bf35,0x3f6d3f35,0xbec43f35,
0x3f6d0000,0x3ec43f80,0xbf6d0000,0xbec4bf80,0xbec43f35,0xbf6dbf35,0x3ec4bf35,0x3f6d3f35,0xbe95bf80,0x3f750000,0xbef13f35,0xbf62bf35,
0x3f463f55,0xbf223f0e,0xbdc9bf7b,0x3f7f3e48,0xbf7fbec4,0x3dc9bf6d,0x3f223f6d,0xbf463ec4,0x3f62be48,0x3ef13f7b,0xbf75bf0e,0x3e95bf55,
0x3e483f80,0xbf7b0000,0x3f7b0000,0x3e483f80,0xbf0ebf6d,0x3f55bec4,0xbf553ec4,0xbf0ebf6d,0x3f553f35,0xbf0e3f35,0x3f0ebf35,0x3f553f35,
0xbf7bbec4,0x3e48bf6d,0xbe483f6d,0xbf7bbec4,0xbdc9bf80,0x3f7f0000,0xbf46bf35,0x3f22bf35,0x3e953f7b,0xbf753e48,0x3f623f0e,0xbef13f55,
0xbef1bf6d,0x3f62bec4,0xbf75bec4,0x3e95bf6d,0x3f223f55,0xbf463f0e,0x3f7f3e48,0xbdc93f7b,0x3f80,0xbf800000,0x3f80,0xbf800000,
0xbf80,0x3f800000,0xbf80,0x3f800000,0x3f80,0xbf800000,0x3f80,0xbf800000,0xbf80,0x3f800000,0xbf80,0x3f800000,
0x3dc9bf80,0x3f7f0000,0x3f46bf35,0x3f223f35,0xbe953f7b,0xbf75be48,0xbf623f0e,0xbef1bf55,0x3ef1bf6d,0x3f623ec4,0x3f75bec4,0x3e953f6d,
0xbf223f55,0xbf46bf0e,0xbf7f3e48,0xbdc9bf7b,0xbe483f80,0xbf7b0000,0xbf7b0000,0x3e48bf80,0x3f0ebf6d,0x3f553ec4,0x3f553ec4,0xbf0e3f6d,
0xbf553f35,0xbf0ebf35,0xbf0ebf35,0x3f55bf35,0x3f7bbec4,0x3e483f6d,0x3e483f6d,0xbf7b3ec4,0x3e95bf80,0x3f750000,0x3ef13f35,0xbf623f35,
0xbf463f55,0xbf22bf0e,0x3dc9bf7b,0x3f7fbe48,0x3f7fbec4,0x3dc93f6d,0xbf223f6d,0xbf46bec4,0xbf62be48,0x3ef1bf7b,0x3f75bf0e,0x3e953f55,
0xbec43f80,0xbf6d0000,0x3ec4bf80,0x3f6d0000,0x3f6dbf35,0x3ec43f35,0xbf6d3f35,0xbec4bf35,0xbf6d0000,0x3ec4bf80,0x3f6d0000,0xbec43f80,
0x3ec43f35,0xbf6d3f35,0xbec4bf35,0x3f6dbf35,0x3ef1bf80,0x3f620000,0xbf753f35,0xbe95bf35,0xbf7f3f0e,0xbdc9bf55,0x3f463e48,0xbf223f7b,
0x3f223ec4,0xbf463f6d,0x3dc9bf6d,0x3f7fbec4,0x3e95bf7b,0x3f75be48,0xbf623f55,0xbef1bf0e,0xbf0e3f80,0xbf550000,0x3f550000,0xbf0e3f80,
0x3f7bbec4,0xbe483f6d,0x3e48bf6d,0x3f7bbec4,0xbe48bf35,0x3f7bbf35,0xbf7b3f35,0xbe48bf35,0xbf553f6d,0xbf0ebec4,0x3f0e3ec4,0xbf553f6d,
0x3f22bf80,0x3f460000,0xbdc9bf35,0x3f7fbf35,0xbf623e48,0x3ef1bf7b,0xbf753f55,0xbe95bf0e,0xbe953f6d,0xbf753ec4,0x3ef13ec4,0xbf623f6d,
0x3f7fbf0e,0xbdc93f55,0x3f46bf7b,0x3f223e48,0xbf353f80,0xbf350000,0xbf353f80,0xbf350000,0x3f350000,0xbf353f80,0x3f350000,0xbf353f80,
0x3f35bf80,0x3f350000,0x3f35bf80,0x3f350000,0xbf350000,0x3f35bf80,0xbf350000,0x3f35bf80,0x3f46bf80,0x3f220000,0x3f7fbf35,0xbdc93f35,
0xbef1be48,0x3f62bf7b,0x3e95bf55,0x3f75bf0e,0xbf753f6d,0xbe95bec4,0xbf623ec4,0x3ef1bf6d,0x3dc93f0e,0xbf7f3f55,0xbf223f7b,0xbf463e48,
0xbf553f80,0xbf0e0000,0xbf0e0000,0x3f55bf80,0x3e483ec4,0xbf7b3f6d,0xbf7b3f6d,0xbe48bec4,0x3f7bbf35,0xbe483f35,0xbe483f35,0xbf7b3f35,
0x3f0ebf6d,0x3f55bec4,0x3f55bec4,0xbf0e3f6d,0x3f62bf80,0x3ef10000,0xbe953f35,0xbf753f35,0x3dc9bf0e,0x3f7fbf55,0x3f22be48,0xbf463f7b,
0xbf463ec4,0x3f22bf6d,0x3f7fbf6d,0x3dc93ec4,0xbf753f7b,0xbe95be48,0x3ef1bf55,0x3f62bf0e,0xbf6d3f80,0xbec40000,0x3f6dbf80,0x3ec40000,
0xbec43f35,0xbf6d3f35,0x3ec4bf35,0x3f6dbf35,0x3ec40000,0xbf6d3f80,0xbec40000,0x3f6dbf80,0x3f6dbf35,0xbec43f35,0xbf6d3f35,0x3ec4bf35,
0x3f75bf80,0x3e950000,0xbf623f35,0x3ef1bf35,0x3f22bf55,0x3f46bf0e,0xbf7f3f7b,0xbdc9be48,0x3dc9bec4,0x3f7fbf6d,0xbf463f6d,0xbf223ec4,
0xbef13e48,0x3f62bf7b,0xbe953f0e,0xbf753f55,0xbf7b3f80,0xbe480000,0x3e480000,0xbf7b3f80,0xbf553f6d,0xbf0e3ec4,0x3f0ebec4,0xbf553f6d,
0xbf0e3f35,0xbf553f35,0x3f55bf35,0xbf0e3f35,0xbe483ec4,0xbf7b3f6d,0x3f7bbf6d,0xbe483ec4,0x3f7fbf80,0x3dc90000,0x3f22bf35,0x3f46bf35,
0x3f75bf7b,0x3e95be48,0x3ef1bf0e,0x3f62bf55,0x3f62bf6d,0x3ef1bec4,0x3e95bec4,0x3f75bf6d,0x3f46bf55,0x3f22bf0e,0x3dc9be48,0x3f7fbf7b,
0x3f803f80,0xbf803f80,0x3f803f80,0xbf803f80,0x3f803f80,0xbf803f80,0x3f803f80,0xbf803f80,0x3f803f80,0xbf803f80,0x3f803f80,0xbf803f80,
0x3f803f80,0xbf803f80,0x3f803f80,0xbf803f80,0x3dc90000,0x3f7f3f80,0x3f463f35,0x3f223f35,0x3e953e48,0x3f753f7b,0x3f623f55,0x3ef13f0e,
0x3ef13ec4,0x3f623f6d,0x3f753f6d,0x3e953ec4,0x3f223f0e,0x3f463f55,0x3f7f3f7b,0x3dc93e48,0xbf7bbf80,0x3e480000,0x3e480000,0x3f7b3f80,
0xbf55bf6d,0x3f0e3ec4,0x3f0e3ec4,0x3f553f6d,0xbf0ebf35,0x3f553f35,0x3f553f35,0x3f0e3f35,0xbe48bec4,0x3f7b3f6d,0x3f7b3f6d,0x3e483ec4,
0xbe950000,0xbf75bf80,0xbef1bf35,0x3f623f35,0xbf46bf0e,0xbf22bf55,0x3dc9be48,0x3f7f3f7b,0xbf7fbf6d,0xbdc9bec4,0x3f223ec4,0x3f463f6d,
0xbf62bf7b,0x3ef13e48,0x3f753f55,0x3e953f0e,0x3f6d3f80,0xbec40000,0xbf6dbf80,0x3ec40000,0x3ec43f35,0xbf6dbf35,0xbec4bf35,0x3f6d3f35,
0xbec40000,0xbf6dbf80,0x3ec40000,0x3f6d3f80,0xbf6dbf35,0xbec4bf35,0x3f6d3f35,0x3ec43f35,0x3ef10000,0x3f623f80,0xbf75bf35,0xbe95bf35,
0x3f7f3f55,0x3dc93f0e,0xbf46bf7b,0x3f223e48,0x3f223f6d,0xbf46bec4,0x3dc9bec4,0x3f7f3f6d,0xbe953e48,0xbf75bf7b,0x3f623f0e,0x3ef13f55,
0xbf55bf80,0x3f0e0000,0xbf0e0000,0xbf55bf80,0x3e48bec4,0x3f7b3f6d,0xbf7bbf6d,0x3e48bec4,0x3f7b3f35,0x3e483f35,0xbe48bf35,0x3f7b3f35,
0x3f0e3f6d,0xbf55bec4,0x3f553ec4,0x3f0e3f6d,0xbf220000,0xbf46bf80,0x3dc93f35,0xbf7fbf35,0xbf62bf7b,0x3ef1be48,0xbf75bf0e,0xbe95bf55,
0x3e95bec4,0x3f753f6d,0xbef1bf6d,0x3f623ec4,0x3f7f3f55,0xbdc93f0e,0x3f463e48,0x3f223f7b,0x3f353f80,0xbf350000,0x3f353f80,0xbf350000,
0xbf350000,0xbf35bf80,0xbf350000,0xbf35bf80,0xbf35bf80,0x3f350000,0xbf35bf80,0x3f350000,0x3f350000,0x3f353f80,0x3f350000,0x3f353f80,
0x3f460000,0x3f223f80,0x3f7f3f35,0xbdc93f35,0x3ef13f7b,0xbf62be48,0xbe953f0e,0xbf75bf55,0xbf75bec4,0xbe95bf6d,0xbf62bf6d,0x3ef1bec4,
0xbdc9bf55,0x3f7f3f0e,0x3f22be48,0x3f463f7b,0xbf0ebf80,0x3f550000,0x3f550000,0x3f0e3f80,0x3f7b3ec4,0x3e483f6d,0x3e483f6d,0xbf7bbec4,
0xbe483f35,0xbf7bbf35,0xbf7bbf35,0x3e48bf35,0xbf55bf6d,0x3f0ebec4,0x3f0ebec4,0x3f553f6d,0xbf620000,0xbef1bf80,0x3e95bf35,0x3f753f35,
0x3dc9bf55,0x3f7f3f0e,0x3f223f7b,0xbf463e48,0x3f463f6d,0xbf223ec4,0xbf7fbec4,0xbdc9bf6d,0xbf75be48,0xbe95bf7b,0x3ef1bf0e,0x3f623f55,
0x3ec43f80,0xbf6d0000,0xbec4bf80,0x3f6d0000,0xbf6dbf35,0x3ec4bf35,0x3f6d3f35,0xbec43f35,0x3f6d0000,0x3ec43f80,0xbf6d0000,0xbec4bf80,
0xbec43f35,0xbf6dbf35,0x3ec4bf35,0x3f6d3f35,0x3f750000,0x3e953f80,0xbf62bf35,0x3ef1bf35,0xbf223f0e,0xbf46bf55,0x3f7f3e48,0x3dc93f7b,
0x3dc9bf6d,0x3f7f3ec4,0xbf463ec4,0xbf22bf6d,0x3ef13f7b,0xbf623e48,0x3e95bf55,0x3f753f0e,0xbe48bf80,0x3f7b0000,0xbf7b0000,0xbe48bf80,
0x3f0e3f6d,0xbf553ec4,0x3f55bec4,0x3f0e3f6d,0xbf55bf35,0x3f0ebf35,0xbf0e3f35,0xbf55bf35,0x3f7b3ec4,0xbe483f6d,0x3e48bf6d,0x3f7b3ec4,
0xbf7f0000,0xbdc9bf80,0xbf223f35,0xbf46bf35,0x3f75be48,0x3e953f7b,0x3ef1bf55,0x3f623f0e,0xbf623ec4,0xbef1bf6d,0xbe953f6d,0xbf75bec4,
0x3f46bf0e,0x3f223f55,0x3dc9bf7b,0x3f7f3e48,0x3f80,0xbf800000,0x3f80,0xbf800000,0xbf80,0x3f800000,0xbf80,0x3f800000,
0x3f80,0xbf800000,0x3f80,0xbf800000,0xbf80,0x3f800000,0xbf80,0x3f800000,0x3f7f0000,0xbdc93f80,0x3f223f35,0xbf463f35,
0xbf75be48,0x3e95bf7b,0xbef1bf55,0x3f62bf0e,0x3f623ec4,0xbef13f6d,0x3e953f6d,0xbf753ec4,0xbf46bf0e,0x3f22bf55,0xbdc9bf7b,0x3f7fbe48,
0x3e48bf80,0x3f7b0000,0x3f7b0000,0xbe483f80,0xbf0e3f6d,0xbf55bec4,0xbf55bec4,0x3f0ebf6d,0x3f55bf35,0x3f0e3f35,0x3f0e3f35,0xbf553f35,
0xbf7b3ec4,0xbe48bf6d,0xbe48bf6d,0x3f7bbec4,0xbf750000,0x3e95bf80,0x3f62bf35,0x3ef13f35,0x3f223f0e,0xbf463f55,0xbf7f3e48,0x3dc9bf7b,
0xbdc9bf6d,0x3f7fbec4,0x3f463ec4,0xbf223f6d,0xbef13f7b,0xbf62be48,0xbe95bf55,0x3f75bf0e,0xbec43f80,0xbf6d0000,0x3ec4bf80,0x3f6d0000,
0x3f6dbf35,0x3ec43f35,0xbf6d3f35,0xbec4bf35,0xbf6d0000,0x3ec4bf80,0x3f6d0000,0xbec43f80,0x3ec43f35,0xbf6d3f35,0xbec4bf35,0x3f6dbf35,
0x3f620000,0xbef13f80,0xbe95bf35,0x3f75bf35,0xbdc9bf55,0x3f7fbf0e,0xbf223f7b,0xbf46be48,0xbf463f6d,0xbf22bec4,0x3f7fbec4,0xbdc93f6d,
0x3f75be48,0xbe953f7b,0xbef1bf0e,0x3f62bf55,0x3f0ebf80,0x3f550000,0xbf550000,0x3f0ebf80,0xbf7b3ec4,0x3e48bf6d,0xbe483f6d,0xbf7b3ec4,
0x3e483f35,0xbf7b3f35,0x3f7bbf35,0x3e483f35,0x3f55bf6d,0x3f0e3ec4,0xbf0ebec4,0x3f55bf6d,0xbf460000,0x3f22bf80,0xbf7f3f35,0xbdc9bf35,
0xbef13f7b,0xbf623e48,0x3e953f0e,0xbf753f55,0x3f75bec4,0xbe953f6d,0x3f62bf6d,0x3ef13ec4,0x3dc9bf55,0x3f7fbf0e,0xbf22be48,0x3f46bf7b,
0xbf353f80,0xbf350000,0xbf353f80,0xbf350000,0x3f350000,0xbf353f80,0x3f350000,0xbf353f80,0x3f35bf80,0x3f350000,0x3f35bf80,0x3f350000,
0xbf350000,0x3f35bf80,0xbf350000,0x3f35bf80,0x3f220000,0xbf463f80,0xbdc93f35,0xbf7f3f35,0x3f62bf7b,0x3ef13e48,0x3f75bf0e,0xbe953f55,
0xbe95bec4,0x3f75bf6d,0x3ef1bf6d,0x3f62bec4,0xbf7f3f55,0xbdc9bf0e,0xbf463e48,0x3f22bf7b,0x3f55bf80,0x3f0e0000,0x3f0e0000,0xbf553f80,
0xbe48bec4,0x3f7bbf6d,0x3f7bbf6d,0x3e483ec4,0xbf7b3f35,0x3e48bf35,0x3e48bf35,0x3f7bbf35,0xbf0e3f6d,0xbf553ec4,0xbf553ec4,0x3f0ebf6d,
0xbef10000,0x3f62bf80,0x3f75bf35,0xbe953f35,0xbf7f3f55,0x3dc9bf0e,0x3f46bf7b,0x3f22be48,0xbf223f6d,0xbf463ec4,0xbdc9bec4,0x3f7fbf6d,
0x3e953e48,0xbf753f7b,0xbf623f0e,0x3ef1bf55,0xbf6d3f80,0xbec40000,0x3f6dbf80,0x3ec40000,0xbec43f35,0xbf6d3f35,0x3ec4bf35,0x3f6dbf35,
0x3ec40000,0xbf6d3f80,0xbec40000,0x3f6dbf80,0x3f6dbf35,0xbec43f35,0xbf6d3f35,0x3ec4bf35,0x3e950000,0xbf753f80,0x3ef1bf35,0x3f62bf35,
0x3f46bf0e,0xbf223f55,0xbdc9be48,0x3f7fbf7b,0x3f7fbf6d,0xbdc93ec4,0xbf223ec4,0x3f46bf6d,0x3f62bf7b,0x3ef1be48,0xbf753f55,0x3e95bf0e,
0x3f7bbf80,0x3e480000,0xbe480000,0x3f7bbf80,0x3f55bf6d,0x3f0ebec4,0xbf0e3ec4,0x3f55bf6d,0x3f0ebf35,0x3f55bf35,0xbf553f35,0x3f0ebf35,
0x3e48bec4,0x3f7bbf6d,0xbf7b3f6d,0x3e48bec4,0xbdc90000,0x3f7fbf80,0xbf463f35,0x3f22bf35,0xbe953e48,0x3f75bf7b,0xbf623f55,0x3ef1bf0e,
0xbef13ec4,0x3f62bf6d,0xbf753f6d,0x3e95bec4,0xbf223f0e,0x3f46bf55,0xbf7f3f7b,0x3dc9be48,0x40003f80,0x3fb53f80,0x3f80,0xbfb53f80,
0x40004000,0xbfb50000,0x0,0xbfb5c000,0x40004000,0xbfb5c000,0x0,0x3fb50000,0x40004000,0x3fb50000,0x0,0x3fb54000,
0x3fff3f80,0x3fa23f80,0xbe49bf80,0xbfc6bf80,0x3ff53ffb,0xbfe2bec8,0xbf15bec8,0xbf71bffb,0x3fe23fed,0xbf15bfed,0xbf71bf44,0x3ff53f44,
0x3fc63fd5,0x3fff3f8e,0xbfa2bf8e,0x3e493fd5,0x3ffb3f80,0x3f8e3f80,0xbec83f80,0xbfd53f80,0x3fd53fed,0xbffbbf44,0xbf8ebf44,0xbec8bfed,
0x3f8e3fb5,0x3ec8bfb5,0xbfd5bfb5,0x3ffb3fb5,0x3ec83f44,0x3fd53fed,0xbffbbfed,0xbf8e3f44,0x3ff53f80,0x3f713f80,0xbf15bf80,0xbfe2bf80,
0x3fa23fd5,0xbfffbf8e,0xbfc6bf8e,0x3e49bfd5,0x3e493f44,0x3fa2bf44,0xbfffbfed,0x3fc63fed,0xbf71bec8,0x3f153ffb,0xbfe2bffb,0xbff5bec8,
0x3fed3f80,0x3f443f80,0xbf443f80,0xbfed3f80,0x3f443fb5,0xbfedbfb5,0xbfedbfb5,0x3f44bfb5,0xbf440000,0x3fed0000,0xbfedc000,0x3f444000,
0xbfedbfb5,0xbf443fb5,0xbf44bfb5,0xbfedbfb5,0x3fe23f80,0x3f153f80,0xbf71bf80,0xbff5bf80,0x3e493f8e,0xbfc6bfd5,0xbfffbfd5,0x3fa2bf8e,
0xbfc6bf44,0x3fff3f44,0xbfa2bfed,0xbe493fed,0xbff5bffb,0xbfe23ec8,0x3f15bec8,0xbf71bffb,0x3fd53f80,0x3ec83f80,0xbf8e3f80,0xbffb3f80,
0xbec83f44,0xbf8ebfed,0xbffbbfed,0x3fd5bf44,0xbffbbfb5,0x3fd53fb5,0xbec8bfb5,0xbf8e3fb5,0xbf8ebfed,0xbffbbf44,0x3fd53f44,0x3ec8bfed,
0x3fc63f80,0x3e493f80,0xbfa2bf80,0xbfffbf80,0xbf713ec8,0xbf15bffb,0xbfe2bffb,0x3ff5bec8,0xbff5bfed,0x3f713fed,0x3f15bf44,0xbfe23f44,
0x3e49bf8e,0xbfa2bfd5,0x3fff3fd5,0x3fc6bf8e,0x3f80,0xbfb53f80,0xc0003f80,0xbfb53f80,0xc000,0x3fb50000,0x40000000,0xbfb54000,
0x4000,0x3fb5c000,0xc0000000,0x3fb50000,0xc000,0xbfb50000,0x40000000,0x3fb5c000,0xbe493f80,0xbfc63f80,0xbfffbf80,0xbfa2bf80,
0x3f15bffb,0x3f713ec8,0x3ff53ec8,0xbfe23ffb,0xbf713fed,0x3ff5bfed,0xbfe2bf44,0x3f153f44,0x3fa2bfd5,0xbe49bf8e,0x3fc63f8e,0x3fffbfd5,
0xbec83f80,0xbfd53f80,0xbffb3f80,0xbf8e3f80,0x3f8ebfed,0x3ec83f44,0x3fd53f44,0xbffb3fed,0xbfd53fb5,0x3ffbbfb5,0xbf8ebfb5,0xbec83fb5,
0x3ffbbf44,0x3f8ebfed,0x3ec83fed,0x3fd5bf44,0xbf153f80,0xbfe23f80,0xbff5bf80,0xbf71bf80,0x3fc6bfd5,0xbe493f8e,0x3fa23f8e,0xbfff3fd5,
0xbfff3f44,0x3fc6bf44,0xbe49bfed,0xbfa23fed,0x3fe23ec8,0x3ff5bffb,0xbf713ffb,0x3f153ec8,0xbf443f80,0xbfed3f80,0xbfed3f80,0xbf443f80,
0x3fedbfb5,0xbf443fb5,0x3f443fb5,0xbfed3fb5,0xbfed0000,0x3f440000,0x3f44c000,0xbfed4000,0x3f443fb5,0x3fedbfb5,0xbfed3fb5,0xbf443fb5,
0xbf713f80,0xbff53f80,0xbfe2bf80,0xbf15bf80,0x3fffbf8e,0xbfa23fd5,0x3e493fd5,0xbfc63f8e,0xbfa2bf44,0xbe493f44,0x3fc6bfed,0xbfff3fed,
0xbf153ffb,0x3f71bec8,0xbff53ec8,0xbfe23ffb,0xbf8e3f80,0xbffb3f80,0xbfd53f80,0xbec83f80,0x3ffbbf44,0xbfd53fed,0xbec83fed,0xbf8e3f44,
0xbec8bfb5,0xbf8e3fb5,0x3ffbbfb5,0xbfd53fb5,0xbfd53fed,0xbec83f44,0xbf8ebf44,0xbffb3fed,0xbfa23f80,0xbfff3f80,0xbfc6bf80,0xbe49bf80,
0x3fe2bec8,0xbff53ffb,0xbf713ffb,0xbf153ec8,0x3f15bfed,0xbfe23fed,0x3ff5bf44,0xbf713f44,0xbfff3f8e,0xbfc63fd5,0x3e49bfd5,0xbfa23f8e,
0xc0003f80,0xbfb53f80,0x3f80,0x3fb53f80,0xc0004000,0x3fb50000,0x0,0x3fb5c000,0xc0004000,0x3fb5c000,0x0,0xbfb50000,
0xc0004000,0xbfb50000,0x0,0xbfb54000,0xbfff3f80,0xbfa23f80,0x3e49bf80,0x3fc6bf80,0xbff53ffb,0x3fe2bec8,0x3f15bec8,0x3f71bffb,
0xbfe23fed,0x3f15bfed,0x3f71bf44,0xbff53f44,0xbfc63fd5,0xbfff3f8e,0x3fa2bf8e,0xbe493fd5,0xbffb3f80,0xbf8e3f80,0x3ec83f80,0x3fd53f80,
0xbfd53fed,0x3ffbbf44,0x3f8ebf44,0x3ec8bfed,0xbf8e3fb5,0xbec8bfb5,0x3fd5bfb5,0xbffb3fb5,0xbec83f44,0xbfd53fed,0x3ffbbfed,0x3f8e3f44,
0xbff53f80,0xbf713f80,0x3f15bf80,0x3fe2bf80,0xbfa23fd5,0x3fffbf8e,0x3fc6bf8e,0xbe49bfd5,0xbe493f44,0xbfa2bf44,0x3fffbfed,0xbfc63fed,
0x3f71bec8,0xbf153ffb,0x3fe2bffb,0x3ff5bec8,0xbfed3f80,0xbf443f80,0x3f443f80,0x3fed3f80,0xbf443fb5,0x3fedbfb5,0x3fedbfb5,0xbf44bfb5,
0x3f440000,0xbfed0000,0x3fedc000,0xbf444000,0x3fedbfb5,0x3f443fb5,0x3f44bfb5,0x3fedbfb5,0xbfe23f80,0xbf153f80,0x3f71bf80,0x3ff5bf80,
0xbe493f8e,0x3fc6bfd5,0x3fffbfd5,0xbfa2bf8e,0x3fc6bf44,0xbfff3f44,0x3fa2bfed,0x3e493fed,0x3ff5bffb,0x3fe23ec8,0xbf15bec8,0x3f71bffb,
0xbfd53f80,0xbec83f80,0x3f8e3f80,0x3ffb3f80,0x3ec83f44,0x3f8ebfed,0x3ffbbfed,0xbfd5bf44,0x3ffbbfb5,0xbfd53fb5,0x3ec8bfb5,0x3f8e3fb5,
0x3f8ebfed,0x3ffbbf44,0xbfd53f44,0xbec8bfed,0xbfc63f80,0xbe493f80,0x3fa2bf80,0x3fffbf80,0x3f713ec8,0x3f15bffb,0x3fe2bffb,0xbff5bec8,
0x3ff5bfed,0xbf713fed,0xbf15bf44,0x3fe23f44,0xbe49bf8e,0x3fa2bfd5,0xbfff3fd5,0xbfc6bf8e,0x3f80,0x3fb53f80,0x40003f80,0x3fb53f80,
0xc000,0xbfb50000,0xc0000000,0x3fb54000,0x4000,0xbfb5c000,0x40000000,0xbfb50000,0xc000,0x3fb50000,0xc0000000,0xbfb5c000,
0x3e493f80,0x3fc63f80,0x3fffbf80,0x3fa2bf80,0xbf15bffb,0xbf713ec8,0xbff53ec8,0x3fe23ffb,0x3f713fed,0xbff5bfed,0x3fe2bf44,0xbf153f44,
0xbfa2bfd5,0x3e49bf8e,0xbfc63f8e,0xbfffbfd5,0x3ec83f80,0x3fd53f80,0x3ffb3f80,0x3f8e3f80,0xbf8ebfed,0xbec83f44,0xbfd53f44,0x3ffb3fed,
0x3fd53fb5,0xbffbbfb5,0x3f8ebfb5,0x3ec83fb5,0xbffbbf44,0xbf8ebfed,0xbec83fed,0xbfd5bf44,0x3f153f80,0x3fe23f80,0x3ff5bf80,0x3f71bf80,
0xbfc6bfd5,0x3e493f8e,0xbfa23f8e,0x3fff3fd5,0x3fff3f44,0xbfc6bf44,0x3e49bfed,0x3fa23fed,0xbfe23ec8,0xbff5bffb,0x3f713ffb,0xbf153ec8,
0x3f443f80,0x3fed3f80,0x3fed3f80,0x3f443f80,0xbfedbfb5,0x3f443fb5,0xbf443fb5,0x3fed3fb5,0x3fed0000,0xbf440000,0xbf44c000,0x3fed4000,
0xbf443fb5,0xbfedbfb5,0x3fed3fb5,0x3f443fb5,0x3f713f80,0x3ff53f80,0x3fe2bf80,0x3f15bf80,0xbfffbf8e,0x3fa23fd5,0xbe493fd5,0x3fc63f8e,
0x3fa2bf44,0x3e493f44,0xbfc6bfed,0x3fff3fed,0x3f153ffb,0xbf71bec8,0x3ff53ec8,0x3fe23ffb,0x3f8e3f80,0x3ffb3f80,0x3fd53f80,0x3ec83f80,
0xbffbbf44,0x3fd53fed,0x3ec83fed,0x3f8e3f44,0x3ec8bfb5,0x3f8e3fb5,0xbffbbfb5,0x3fd53fb5,0x3fd53fed,0x3ec83f44,0x3f8ebf44,0x3ffb3fed,
0x3fa23f80,0x3fff3f80,0x3fc6bf80,0x3e49bf80,0xbfe2bec8,0x3ff53ffb,0x3f713ffb,0x3f153ec8,0xbf15bfed,0x3fe23fed,0xbff5bf44,0x3f713f44,
0x3fff3f8e,0x3fc63fd5,0xbe49bfd5,0x3fa23f8e,0x40004000,0x3fb54000,0x0,0xbfb50000,0x40004000,0xbfb50000,0x0,0xbfb5c000,
0x40004000,0xbfb5c000,0x0,0x3fb50000,0x40004000,0x3fb50000,0x0,0x3fb54000,0x3fa23fb5,0xbe493fb5,0xbfc6bfb5,0xbfffbfb5,
0x3f713f8e,0xbff5bfd5,0xbfe2bfd5,0x3f15bf8e,0x3f153f44,0x3f71bf44,0xbff5bfed,0x3fe23fed,0x3e493ec8,0x3fc63ffb,0xbfffbffb,0xbfa23ec8,
0xbec80000,0xbfd50000,0xbffbc000,0xbf8ec000,0xbf8ebf44,0xbec8bfed,0xbfd5bfed,0x3ffb3f44,0xbfd5bfb5,0x3ffb3fb5,0xbf8ebfb5,0xbec83fb5,
0xbffbbfed,0xbf8e3f44,0xbec8bf44,0xbfd5bfed,0xbfe2bfb5,0xbff5bfb5,0xbf71bfb5,0x3f15bfb5,0xbfffbffb,0x3fc6bec8,0x3e49bec8,0x3fa23ffb,
0xbfc6bfed,0x3e493fed,0x3fa23f44,0xbfffbf44,0xbf15bf8e,0xbfe2bfd5,0x3ff53fd5,0x3f71bf8e,0xbfedc000,0xbf44c000,0x3f440000,0x3fed0000,
0xbf44bfb5,0x3fed3fb5,0x3fed3fb5,0xbf443fb5,0x3f440000,0xbfed0000,0x3fed4000,0xbf44c000,0x3fed3fb5,0x3f44bfb5,0x3f443fb5,0x3fed3fb5,
0xbf15bfb5,0x3f71bfb5,0x3ff53fb5,0x3fe23fb5,0x3fa23ec8,0x3e493ffb,0x3fc63ffb,0xbfffbec8,0x3fff3fed,0xbfa2bfed,0xbe493f44,0x3fc6bf44,
0x3f713fd5,0x3ff53f8e,0xbfe2bf8e,0xbf153fd5,0x3f8e0000,0x3ffb0000,0x3fd54000,0x3ec84000,0x3ffb3fed,0xbfd53f44,0xbec83f44,0xbf8ebfed,
0x3ec83fb5,0x3f8ebfb5,0xbffbbfb5,0x3fd53fb5,0xbfd5bf44,0xbec83fed,0xbf8ebfed,0xbffbbf44,0x3fff3fb5,0x3fc63fb5,0x3e493fb5,0xbfa23fb5,
0x3f153fd5,0xbfe2bf8e,0xbff5bf8e,0x3f71bfd5,0xbfe2bf44,0x3ff53f44,0xbf71bfed,0xbf153fed,0xbfa2bffb,0xbfffbec8,0x3fc63ec8,0x3e49bffb,
0x4000,0xbfb54000,0xc0000000,0xbfb50000,0xc000,0x3fb50000,0x40000000,0xbfb54000,0x4000,0x3fb5c000,0xc0000000,0x3fb50000,
0xc000,0xbfb50000,0x40000000,0x3fb5c000,0xbfc63fb5,0xbfff3fb5,0xbfa2bfb5,0x3e49bfb5,0x3fe2bf8e,0xbf153fd5,0x3f713fd5,0xbff53f8e,
0xbff53f44,0x3fe2bf44,0xbf15bfed,0xbf713fed,0x3fffbec8,0x3fa2bffb,0x3e493ffb,0x3fc6bec8,0xbffb0000,0xbf8e0000,0x3ec8c000,0x3fd5c000,
0x3fd53f44,0xbffb3fed,0xbf8e3fed,0xbec8bf44,0xbf8ebfb5,0xbec83fb5,0x3fd5bfb5,0xbffb3fb5,0x3ec83fed,0x3fd5bf44,0xbffb3f44,0xbf8e3fed,
0xbf71bfb5,0x3f15bfb5,0x3fe2bfb5,0x3ff5bfb5,0xbe493ffb,0xbfa23ec8,0xbfff3ec8,0x3fc6bffb,0x3fa2bfed,0xbfff3fed,0x3fc63f44,0xbe49bf44,
0xbff53f8e,0xbf713fd5,0xbf15bfd5,0xbfe23f8e,0x3f44c000,0x3fedc000,0x3fed0000,0x3f440000,0xbfed3fb5,0x3f44bfb5,0xbf44bfb5,0x3fedbfb5,
0x3fed0000,0xbf440000,0xbf444000,0x3fedc000,0xbf44bfb5,0xbfed3fb5,0x3fedbfb5,0x3f44bfb5,0x3ff5bfb5,0x3fe2bfb5,0x3f153fb5,0xbf713fb5,
0xbfc6bec8,0x3fffbffb,0x3fa2bffb,0x3e493ec8,0xbe493fed,0x3fc6bfed,0xbfff3f44,0x3fa2bf44,0x3fe2bfd5,0x3f15bf8e,0x3f713f8e,0x3ff5bfd5,
0x3fd50000,0x3ec80000,0xbf8e4000,0xbffb4000,0x3ec8bfed,0x3f8ebf44,0x3ffbbf44,0xbfd53fed,0xbffb3fb5,0x3fd5bfb5,0xbec8bfb5,0xbf8e3fb5,
0x3f8e3f44,0x3ffbbfed,0xbfd53fed,0xbec83f44,0x3e493fb5,0xbfa23fb5,0xbfff3fb5,0xbfc63fb5,0x3ff5bfd5,0xbf713f8e,0x3f153f8e,0xbfe23fd5,
0xbf71bf44,0xbf153f44,0x3fe2bfed,0xbff53fed,0xbfc63ffb,0xbe493ec8,0xbfa2bec8,0xbfff3ffb,0xc0004000,0xbfb54000,0x0,0x3fb50000,
0xc0004000,0x3fb50000,0x0,0x3fb5c000,0xc0004000,0x3fb5c000,0x0,0xbfb50000,0xc0004000,0xbfb50000,0x0,0xbfb54000,
0xbfa23fb5,0x3e493fb5,0x3fc6bfb5,0x3fffbfb5,0xbf713f8e,0x3ff5bfd5,0x3fe2bfd5,0xbf15bf8e,0xbf153f44,0xbf71bf44,0x3ff5bfed,0xbfe23fed,
0xbe493ec8,0xbfc63ffb,0x3fffbffb,0x3fa23ec8,0x3ec80000,0x3fd50000,0x3ffbc000,0x3f8ec000,0x3f8ebf44,0x3ec8bfed,0x3fd5bfed,0xbffb3f44,
0x3fd5bfb5,0xbffb3fb5,0x3f8ebfb5,0x3ec83fb5,0x3ffbbfed,0x3f8e3f44,0x3ec8bf44,0x3fd5bfed,0x3fe2bfb5,0x3ff5bfb5,0x3f71bfb5,0xbf15bfb5,
0x3fffbffb,0xbfc6bec8,0xbe49bec8,0xbfa23ffb,0x3fc6bfed,0xbe493fed,0xbfa23f44,0x3fffbf44,0x3f15bf8e,0x3fe2bfd5,0xbff53fd5,0xbf71bf8e,
0x3fedc000,0x3f44c000,0xbf440000,0xbfed0000,0x3f44bfb5,0xbfed3fb5,0xbfed3fb5,0x3f443fb5,0xbf440000,0x3fed0000,0xbfed4000,0x3f44c000,
0xbfed3fb5,0xbf44bfb5,0xbf443fb5,0xbfed3fb5,0x3f15bfb5,0xbf71bfb5,0xbff53fb5,0xbfe23fb5,0xbfa23ec8,0xbe493ffb,0xbfc63ffb,0x3fffbec8,
0xbfff3fed,0x3fa2bfed,0x3e493f44,0xbfc6bf44,0xbf713fd5,0xbff53f8e,0x3fe2bf8e,0x3f153fd5,0xbf8e0000,0xbffb0000,0xbfd54000,0xbec84000,
0xbffb3fed,0x3fd53f44,0x3ec83f44,0x3f8ebfed,0xbec83fb5,0xbf8ebfb5,0x3ffbbfb5,0xbfd53fb5,0x3fd5bf44,0x3ec83fed,0x3f8ebfed,0x3ffbbf44,
0xbfff3fb5,0xbfc63fb5,0xbe493fb5,0x3fa23fb5,0xbf153fd5,0x3fe2bf8e,0x3ff5bf8e,0xbf71bfd5,0x3fe2bf44,0xbff53f44,0x3f71bfed,0x3f153fed,
0x3fa2bffb,0x3fffbec8,0xbfc63ec8,0xbe49bffb,0x4000,0x3fb54000,0x40000000,0x3fb50000,0xc000,0xbfb50000,0xc0000000,0x3fb54000,
0x4000,0xbfb5c000,0x40000000,0xbfb50000,0xc000,0x3fb50000,0xc0000000,0xbfb5c000,0x3fc63fb5,0x3fff3fb5,0x3fa2bfb5,0xbe49bfb5,
0xbfe2bf8e,0x3f153fd5,0xbf713fd5,0x3ff53f8e,0x3ff53f44,0xbfe2bf44,0x3f15bfed,0x3f713fed,0xbfffbec8,0xbfa2bffb,0xbe493ffb,0xbfc6bec8,
0x3ffb0000,0x3f8e0000,0xbec8c000,0xbfd5c000,0xbfd53f44,0x3ffb3fed,0x3f8e3fed,0x3ec8bf44,0x3f8ebfb5,0x3ec83fb5,0xbfd5bfb5,0x3ffb3fb5,
0xbec83fed,0xbfd5bf44,0x3ffb3f44,0x3f8e3fed,0x3f71bfb5,0xbf15bfb5,0xbfe2bfb5,0xbff5bfb5,0x3e493ffb,0x3fa23ec8,0x3fff3ec8,0xbfc6bffb,
0xbfa2bfed,0x3fff3fed,0xbfc63f44,0x3e49bf44,0x3ff53f8e,0x3f713fd5,0x3f15bfd5,0x3fe23f8e,0xbf44c000,0xbfedc000,0xbfed0000,0xbf440000,
0x3fed3fb5,0xbf44bfb5,0x3f44bfb5,0xbfedbfb5,0xbfed0000,0x3f440000,0x3f444000,0xbfedc000,0x3f44bfb5,0x3fed3fb5,0xbfedbfb5,0xbf44bfb5,
0xbff5bfb5,0xbfe2bfb5,0xbf153fb5,0x3f713fb5,0x3fc6bec8,0xbfffbffb,0xbfa2bffb,0xbe493ec8,0x3e493fed,0xbfc6bfed,0x3fff3f44,0xbfa2bf44,
0xbfe2bfd5,0xbf15bf8e,0xbf713f8e,0xbff5bfd5,0xbfd50000,0xbec80000,0x3f8e4000,0x3ffb4000,0xbec8bfed,0xbf8ebf44,0xbffbbf44,0x3fd53fed,
0x3ffb3fb5,0xbfd5bfb5,0x3ec8bfb5,0x3f8e3fb5,0xbf8e3f44,0xbffbbfed,0x3fd53fed,0x3ec83f44,0xbe493fb5,0x3fa23fb5,0x3fff3fb5,0x3fc63fb5,
0xbff5bfd5,0x3f713f8e,0xbf153f8e,0x3fe23fd5,0x3f71bf44,0x3f153f44,0xbfe2bfed,0x3ff53fed,0x3fc63ffb,0x3e493ec8,0x3fa2bec8,0x3fff3ffb,
0x40004000,0x3fb54000,0x0,0xbfb50000,0x40004000,0xbfb50000,0x0,0xbfb5c000,0x40004000,0xbfb5c000,0x0,0x3fb50000,
0x40004000,0x3fb50000,0x0,0x3fb54000,0xbe490000,0xbfc60000,0xbfffc000,0xbfa2c000,0xbf15bec8,0xbf71bffb,0xbff5bffb,0x3fe23ec8,
0xbf71bf44,0x3ff53f44,0xbfe2bfed,0x3f153fed,0xbfa2bf8e,0x3e493fd5,0xbfc6bfd5,0xbfffbf8e,0xbffbc000,0xbf8ec000,0x3ec80000,0x3fd50000,
0xbfd5bfed,0x3ffb3f44,0x3f8e3f44,0x3ec83fed,0xbf8ebfb5,0xbec83fb5,0x3fd53fb5,0xbffbbfb5,0xbec8bf44,0xbfd5bfed,0x3ffb3fed,0x3f8ebf44,
0x3f150000,0x3fe20000,0x3ff54000,0x3f714000,0x3fc63f8e,0xbe493fd5,0x3fa23fd5,0xbfffbf8e,0x3fff3fed,0xbfc6bfed,0x3e493f44,0x3fa2bf44,
0x3fe23ffb,0x3ff53ec8,0xbf71bec8,0x3f153ffb,0x3fed4000,0x3f444000,0xbf440000,0xbfed0000,0x3f443fb5,0xbfedbfb5,0xbfedbfb5,0x3f44bfb5,
0xbf440000,0x3fed0000,0xbfedc000,0x3f444000,0xbfedbfb5,0xbf443fb5,0xbf44bfb5,0xbfedbfb5,0xbf710000,0xbff50000,0xbfe2c000,0xbf15c000,
0xbfffbfd5,0x3fa2bf8e,0xbe49bf8e,0x3fc63fd5,0xbfa2bfed,0xbe493fed,0x3fc63f44,0xbfffbf44,0x3f15bec8,0xbf71bffb,0x3ff53ffb,0x3fe2bec8,
0xbfd5c000,0xbec8c000,0x3f8e0000,0x3ffb0000,0x3ec8bf44,0x3f8e3fed,0x3ffb3fed,0xbfd53f44,0x3ffb3fb5,0xbfd5bfb5,0x3ec83fb5,0x3f8ebfb5,
0x3f8e3fed,0x3ffb3f44,0xbfd5bf44,0xbec83fed,0x3fa20000,0x3fff0000,0x3fc64000,0x3e494000,0x3fe23ffb,0xbff53ec8,0xbf713ec8,0xbf15bffb,
0xbf153f44,0x3fe2bf44,0xbff5bfed,0x3f713fed,0xbfffbfd5,0xbfc63f8e,0x3e49bf8e,0xbfa2bfd5,0x4000,0xbfb54000,0xc0000000,0xbfb50000,
0xc000,0x3fb50000,0x40000000,0xbfb54000,0x4000,0x3fb5c000,0xc0000000,0x3fb50000,0xc000,0xbfb50000,0x40000000,0x3fb5c000,
0xbfff0000,0xbfa20000,0x3e49c000,0x3fc6c000,0x3ff53ec8,0xbfe23ffb,0xbf153ffb,0xbf71bec8,0xbfe2bf44,0x3f153f44,0x3f71bfed,0xbff53fed,
0x3fc63f8e,0x3fffbfd5,0xbfa23fd5,0x3e493f8e,0x3ec8c000,0x3fd5c000,0x3ffb0000,0x3f8e0000,0xbf8e3fed,0xbec8bf44,0xbfd5bf44,0x3ffbbfed,
0x3fd5bfb5,0xbffb3fb5,0x3f8e3fb5,0x3ec8bfb5,0xbffb3f44,0xbf8e3fed,0xbec8bfed,0xbfd53f44,0x3ff50000,0x3f710000,0xbf154000,0xbfe24000,
0xbfa2bf8e,0x3fffbfd5,0x3fc6bfd5,0xbe493f8e,0x3e493fed,0x3fa2bfed,0xbfff3f44,0x3fc6bf44,0x3f71bffb,0xbf15bec8,0x3fe23ec8,0x3ff5bffb,
0xbf444000,0xbfed4000,0xbfed0000,0xbf440000,0x3fedbfb5,0xbf443fb5,0x3f443fb5,0xbfed3fb5,0xbfed0000,0x3f440000,0x3f44c000,0xbfed4000,
0x3f443fb5,0x3fedbfb5,0xbfed3fb5,0xbf443fb5,0xbfe20000,0xbf150000,0x3f71c000,0x3ff5c000,0x3e493fd5,0xbfc63f8e,0xbfff3f8e,0x3fa2bfd5,
0x3fc6bfed,0xbfff3fed,0x3fa23f44,0x3e49bf44,0xbff53ec8,0xbfe23ffb,0x3f15bffb,0xbf713ec8,0x3f8ec000,0x3ffbc000,0x3fd50000,0x3ec80000,
0xbffb3f44,0x3fd5bfed,0x3ec8bfed,0x3f8ebf44,0x3ec83fb5,0x3f8ebfb5,0xbffb3fb5,0x3fd5bfb5,0x3fd5bfed,0x3ec8bf44,0x3f8e3f44,0x3ffbbfed,
0x3fc60000,0x3e490000,0xbfa24000,0xbfff4000,0x3f71bffb,0x3f15bec8,0x3fe2bec8,0xbff53ffb,0xbff53f44,0x3f71bf44,0x3f15bfed,0xbfe23fed,
0xbe493fd5,0x3fa2bf8e,0xbfff3f8e,0xbfc63fd5,0xc0004000,0xbfb54000,0x0,0x3fb50000,0xc0004000,0x3fb50000,0x0,0x3fb5c000,
0xc0004000,0x3fb5c000,0x0,0xbfb50000,0xc0004000,0xbfb50000,0x0,0xbfb54000,0x3e490000,0x3fc60000,0x3fffc000,0x3fa2c000,
0x3f15bec8,0x3f71bffb,0x3ff5bffb,0xbfe23ec8,0x3f71bf44,0xbff53f44,0x3fe2bfed,0xbf153fed,0x3fa2bf8e,0xbe493fd5,0x3fc6bfd5,0x3fffbf8e,
0x3ffbc000,0x3f8ec000,0xbec80000,0xbfd50000,0x3fd5bfed,0xbffb3f44,0xbf8e3f44,0xbec83fed,0x3f8ebfb5,0x3ec83fb5,0xbfd53fb5,0x3ffbbfb5,
0x3ec8bf44,0x3fd5bfed,0xbffb3fed,0xbf8ebf44,0xbf150000,0xbfe20000,0xbff54000,0xbf714000,0xbfc63f8e,0x3e493fd5,0xbfa23fd5,0x3fffbf8e,
0xbfff3fed,0x3fc6bfed,0xbe493f44,0xbfa2bf44,0xbfe23ffb,0xbff53ec8,0x3f71bec8,0xbf153ffb,0xbfed4000,0xbf444000,0x3f440000,0x3fed0000,
0xbf443fb5,0x3fedbfb5,0x3fedbfb5,0xbf44bfb5,0x3f440000,0xbfed0000,0x3fedc000,0xbf444000,0x3fedbfb5,0x3f443fb5,0x3f44bfb5,0x3fedbfb5,
0x3f710000,0x3ff50000,0x3fe2c000,0x3f15c000,0x3fffbfd5,0xbfa2bf8e,0x3e49bf8e,0xbfc63fd5,0x3fa2bfed,0x3e493fed,0xbfc63f44,0x3fffbf44,
0xbf15bec8,0x3f71bffb,0xbff53ffb,0xbfe2bec8,0x3fd5c000,0x3ec8c000,0xbf8e0000,0xbffb0000,0xbec8bf44,0xbf8e3fed,0xbffb3fed,0x3fd53f44,
0xbffb3fb5,0x3fd5bfb5,0xbec83fb5,0xbf8ebfb5,0xbf8e3fed,0xbffb3f44,0x3fd5bf44,0x3ec83fed,0xbfa20000,0xbfff0000,0xbfc64000,0xbe494000,
0xbfe23ffb,0x3ff53ec8,0x3f713ec8,0x3f15bffb,0x3f153f44,0xbfe2bf44,0x3ff5bfed,0xbf713fed,0x3fffbfd5,0x3fc63f8e,0xbe49bf8e,0x3fa2bfd5,
0x4000,0x3fb54000,0x40000000,0x3fb50000,0xc000,0xbfb50000,0xc0000000,0x3fb54000,0x4000,0xbfb5c000,0x40000000,0xbfb50000,
0xc000,0x3fb50000,0xc0000000,0xbfb5c000,0x3fff0000,0x3fa20000,0xbe49c000,0xbfc6c000,0xbff53ec8,0x3fe23ffb,0x3f153ffb,0x3f71bec8,
0x3fe2bf44,0xbf153f44,0xbf71bfed,0x3ff53fed,0xbfc63f8e,0xbfffbfd5,0x3fa23fd5,0xbe493f8e,0xbec8c000,0xbfd5c000,0xbffb0000,0xbf8e0000,
0x3f8e3fed,0x3ec8bf44,0x3fd5bf44,0xbffbbfed,0xbfd5bfb5,0x3ffb3fb5,0xbf8e3fb5,0xbec8bfb5,0x3ffb3f44,0x3f8e3fed,0x3ec8bfed,0x3fd53f44,
0xbff50000,0xbf710000,0x3f154000,0x3fe24000,0x3fa2bf8e,0xbfffbfd5,0xbfc6bfd5,0x3e493f8e,0xbe493fed,0xbfa2bfed,0x3fff3f44,0xbfc6bf44,
0xbf71bffb,0x3f15bec8,0xbfe23ec8,0xbff5bffb,0x3f444000,0x3fed4000,0x3fed0000,0x3f440000,0xbfedbfb5,0x3f443fb5,0xbf443fb5,0x3fed3fb5,
0x3fed0000,0xbf440000,0xbf44c000,0x3fed4000,0xbf443fb5,0xbfedbfb5,0x3fed3fb5,0x3f443fb5,0x3fe20000,0x3f150000,0xbf71c000,0xbff5c000,
0xbe493fd5,0x3fc63f8e,0x3fff3f8e,0xbfa2bfd5,0xbfc6bfed,0x3fff3fed,0xbfa23f44,0xbe49bf44,0x3ff53ec8,0x3fe23ffb,0xbf15bffb,0x3f713ec8,
0xbf8ec000,0xbffbc000,0xbfd50000,0xbec80000,0x3ffb3f44,0xbfd5bfed,0xbec8bfed,0xbf8ebf44,0xbec83fb5,0xbf8ebfb5,0x3ffb3fb5,0xbfd5bfb5,
0xbfd5bfed,0xbec8bf44,0xbf8e3f44,0xbffbbfed,0xbfc60000,0xbe490000,0x3fa24000,0x3fff4000,0xbf71bffb,0xbf15bec8,0xbfe2bec8,0x3ff53ffb,
0x3ff53f44,0xbf71bf44,0xbf15bfed,0x3fe23fed,0x3e493fd5,0xbfa2bf8e,0x3fff3f8e,0x3fc63fd5,0x40004000,0x3fb54000,0x0,0xbfb50000,
0x40004000,0xbfb50000,0x0,0xbfb5c000,0x40004000,0xbfb5c000,0x0,0x3fb50000,0x40004000,0x3fb50000,0x0,0x3fb54000,
0xbfc6bfb5,0xbfffbfb5,0xbfa2bfb5,0x3e49bfb5,0xbfe2bfd5,0x3f15bf8e,0xbf71bf8e,0x3ff53fd5,0xbff5bfed,0x3fe23fed,0xbf15bf44,0xbf713f44,
0xbfffbffb,0xbfa23ec8,0xbe49bec8,0xbfc6bffb,0x3ec80000,0x3fd50000,0x3ffb4000,0x3f8e4000,0x3f8e3f44,0x3ec83fed,0x3fd53fed,0xbffbbf44,
0x3fd53fb5,0xbffbbfb5,0x3f8e3fb5,0x3ec8bfb5,0x3ffb3fed,0x3f8ebf44,0x3ec83f44,0x3fd53fed,0x3f713fb5,0xbf153fb5,0xbfe2bfb5,0xbff5bfb5,
0xbe493ec8,0xbfa2bffb,0xbfffbffb,0x3fc6bec8,0xbfa2bf44,0x3fff3f44,0xbfc6bfed,0x3e493fed,0xbff5bfd5,0xbf713f8e,0xbf15bf8e,0xbfe2bfd5,
0xbfedc000,0xbf44c000,0x3f440000,0x3fed0000,0xbf44bfb5,0x3fed3fb5,0x3fed3fb5,0xbf443fb5,0x3f440000,0xbfed0000,0x3fed4000,0xbf44c000,
0x3fed3fb5,0x3f44bfb5,0x3f443fb5,0x3fed3fb5,0x3ff53fb5,0x3fe23fb5,0x3f153fb5,0xbf713fb5,0x3fc63ffb,0xbfffbec8,0xbfa2bec8,0xbe49bffb,
0xbe493f44,0x3fc6bf44,0xbfffbfed,0x3fa23fed,0xbfe2bf8e,0xbf153fd5,0xbf71bfd5,0xbff5bf8e,0xbf8e0000,0xbffb0000,0xbfd5c000,0xbec8c000,
0xbffbbfed,0x3fd5bf44,0x3ec8bf44,0x3f8e3fed,0xbec8bfb5,0xbf8e3fb5,0x3ffb3fb5,0xbfd5bfb5,0x3fd53f44,0x3ec8bfed,0x3f8e3fed,0x3ffb3f44,
0xbe49bfb5,0x3fa2bfb5,0x3fff3fb5,0x3fc63fb5,0x3ff53f8e,0xbf713fd5,0x3f153fd5,0xbfe2bf8e,0x3f713fed,0x3f15bfed,0xbfe2bf44,0x3ff53f44,
0xbfc6bec8,0xbe493ffb,0xbfa2bffb,0xbfffbec8,0x4000,0xbfb54000,0xc0000000,0xbfb50000,0xc000,0x3fb50000,0x40000000,0xbfb54000,
0x4000,0x3fb5c000,0xc0000000,0x3fb50000,0xc000,0xbfb50000,0x40000000,0x3fb5c000,0xbfa2bfb5,0x3e49bfb5,0x3fc6bfb5,0x3fffbfb5,
0x3f713fd5,0xbff53f8e,0xbfe23f8e,0x3f15bfd5,0xbf15bfed,0xbf713fed,0x3ff5bf44,0xbfe23f44,0x3e493ffb,0x3fc6bec8,0xbfff3ec8,0xbfa23ffb,
0x3ffb0000,0x3f8e0000,0xbec84000,0xbfd54000,0xbfd5bf44,0x3ffbbfed,0x3f8ebfed,0x3ec83f44,0x3f8e3fb5,0x3ec8bfb5,0xbfd53fb5,0x3ffbbfb5,
0xbec8bfed,0xbfd53f44,0x3ffbbf44,0x3f8ebfed,0xbfe23fb5,0xbff53fb5,0xbf71bfb5,0x3f15bfb5,0x3fffbec8,0xbfc63ffb,0xbe493ffb,0xbfa23ec8,
0xbfc6bf44,0x3e493f44,0x3fa2bfed,0xbfff3fed,0x3f153fd5,0x3fe2bf8e,0xbff53f8e,0xbf713fd5,0x3f44c000,0x3fedc000,0x3fed0000,0x3f440000,
0xbfed3fb5,0x3f44bfb5,0xbf44bfb5,0x3fedbfb5,0x3fed0000,0xbf440000,0xbf444000,0x3fedc000,0xbf44bfb5,0xbfed3fb5,0x3fedbfb5,0x3f44bfb5,
0x3f153fb5,0xbf713fb5,0xbff53fb5,0xbfe23fb5,0x3fa2bffb,0x3e493ec8,0x3fc63ec8,0xbfff3ffb,0xbfff3f44,0x3fa2bf44,0x3e49bfed,0xbfc63fed,
0x3f713f8e,0x3ff5bfd5,0xbfe23fd5,0xbf153f8e,0xbfd50000,0xbec80000,0x3f8ec000,0x3ffbc000,0xbec83fed,0xbf8e3f44,0xbffb3f44,0x3fd5bfed,
0x3ffbbfb5,0xbfd53fb5,0x3ec83fb5,0x3f8ebfb5,0xbf8ebf44,0xbffb3fed,0x3fd5bfed,0x3ec8bf44,0x3fffbfb5,0x3fc6bfb5,0x3e493fb5,0xbfa23fb5,
0xbf15bf8e,0x3fe2bfd5,0x3ff5bfd5,0xbf713f8e,0xbfe23fed,0x3ff5bfed,0xbf71bf44,0xbf153f44,0x3fa23ec8,0x3fffbffb,0xbfc63ffb,0xbe493ec8,
0xc0004000,0xbfb54000,0x0,0x3fb50000,0xc0004000,0x3fb50000,0x0,0x3fb5c000,0xc0004000,0x3fb5c000,0x0,0xbfb50000,
0xc0004000,0xbfb50000,0x0,0xbfb54000,0x3fc6bfb5,0x3fffbfb5,0x3fa2bfb5,0xbe49bfb5,0x3fe2bfd5,0xbf15bf8e,0x3f71bf8e,0xbff53fd5,
0x3ff5bfed,0xbfe23fed,0x3f15bf44,0x3f713f44,0x3fffbffb,0x3fa23ec8,0x3e49bec8,0x3fc6bffb,0xbec80000,0xbfd50000,0xbffb4000,0xbf8e4000,
0xbf8e3f44,0xbec83fed,0xbfd53fed,0x3ffbbf44,0xbfd53fb5,0x3ffbbfb5,0xbf8e3fb5,0xbec8bfb5,0xbffb3fed,0xbf8ebf44,0xbec83f44,0xbfd53fed,
0xbf713fb5,0x3f153fb5,0x3fe2bfb5,0x3ff5bfb5,0x3e493ec8,0x3fa2bffb,0x3fffbffb,0xbfc6bec8,0x3fa2bf44,0xbfff3f44,0x3fc6bfed,0xbe493fed,
0x3ff5bfd5,0x3f713f8e,0x3f15bf8e,0x3fe2bfd5,0x3fedc000,0x3f44c000,0xbf440000,0xbfed0000,0x3f44bfb5,0xbfed3fb5,0xbfed3fb5,0x3f443fb5,
0xbf440000,0x3fed0000,0xbfed4000,0x3f44c000,0xbfed3fb5,0xbf44bfb5,0xbf443fb5,0xbfed3fb5,0xbff53fb5,0xbfe23fb5,0xbf153fb5,0x3f713fb5,
0xbfc63ffb,0x3fffbec8,0x3fa2bec8,0x3e49bffb,0x3e493f44,0xbfc6bf44,0x3fffbfed,0xbfa23fed,0x3fe2bf8e,0x3f153fd5,0x3f71bfd5,0x3ff5bf8e,
0x3f8e0000,0x3ffb0000,0x3fd5c000,0x3ec8c000,0x3ffbbfed,0xbfd5bf44,0xbec8bf44,0xbf8e3fed,0x3ec8bfb5,0x3f8e3fb5,0xbffb3fb5,0x3fd5bfb5,
0xbfd53f44,0xbec8bfed,0xbf8e3fed,0xbffb3f44,0x3e49bfb5,0xbfa2bfb5,0xbfff3fb5,0xbfc63fb5,0xbff53f8e,0x3f713fd5,0xbf153fd5,0x3fe2bf8e,
0xbf713fed,0xbf15bfed,0x3fe2bf44,0xbff53f44,0x3fc6bec8,0x3e493ffb,0x3fa2bffb,0x3fffbec8,0x4000,0x3fb54000,0x40000000,0x3fb50000,
0xc000,0xbfb50000,0xc0000000,0x3fb54000,0x4000,0xbfb5c000,0x40000000,0xbfb50000,0xc000,0x3fb50000,0xc0000000,0xbfb5c000,
0x3fa2bfb5,0xbe49bfb5,0xbfc6bfb5,0xbfffbfb5,0xbf713fd5,0x3ff53f8e,0x3fe23f8e,0xbf15bfd5,0x3f15bfed,0x3f713fed,0xbff5bf44,0x3fe23f44,
0xbe493ffb,0xbfc6bec8,0x3fff3ec8,0x3fa23ffb,0xbffb0000,0xbf8e0000,0x3ec84000,0x3fd54000,0x3fd5bf44,0xbffbbfed,0xbf8ebfed,0xbec83f44,
0xbf8e3fb5,0xbec8bfb5,0x3fd53fb5,0xbffbbfb5,0x3ec8bfed,0x3fd53f44,0xbffbbf44,0xbf8ebfed,0x3fe23fb5,0x3ff53fb5,0x3f71bfb5,0xbf15bfb5,
0xbfffbec8,0x3fc63ffb,0x3e493ffb,0x3fa23ec8,0x3fc6bf44,0xbe493f44,0xbfa2bfed,0x3fff3fed,0xbf153fd5,0xbfe2bf8e,0x3ff53f8e,0x3f713fd5,
0xbf44c000,0xbfedc000,0xbfed0000,0xbf440000,0x3fed3fb5,0xbf44bfb5,0x3f44bfb5,0xbfedbfb5,0xbfed0000,0x3f440000,0x3f444000,0xbfedc000,
0x3f44bfb5,0x3fed3fb5,0xbfedbfb5,0xbf44bfb5,0xbf153fb5,0x3f713fb5,0x3ff53fb5,0x3fe23fb5,0xbfa2bffb,0xbe493ec8,0xbfc63ec8,0x3fff3ffb,
0x3fff3f44,0xbfa2bf44,0xbe49bfed,0x3fc63fed,0xbf713f8e,0xbff5bfd5,0x3fe23fd5,0x3f153f8e,0x3fd50000,0x3ec80000,0xbf8ec000,0xbffbc000,
0x3ec83fed,0x3f8e3f44,0x3ffb3f44,0xbfd5bfed,0xbffbbfb5,0x3fd53fb5,0xbec83fb5,0xbf8ebfb5,0x3f8ebf44,0x3ffb3fed,0xbfd5bfed,0xbec8bf44,
0xbfffbfb5,0xbfc6bfb5,0xbe493fb5,0x3fa23fb5,0x3f15bf8e,0xbfe2bfd5,0xbff5bfd5,0x3f713f8e,0x3fe23fed,0xbff5bfed,0x3f71bf44,0x3f153f44,
0xbfa23ec8,0xbfffbffb,0x3fc63ffb,0x3e493ec8,0x80003f80,0x3f800000,0x80003f80,0x3f800000,0x80003f80,0x3f800000,0x80003f80,0x3f800000,
0x80003f80,0x3f800000,0x80003f80,0x3f800000,0x80003f80,0x3f800000,0x80003f80,0x3f800000,0x80003f80,0x3f800000,0x8000bf80,0xbf800000,
0x3f353f35,0x3f35bf35,0xbf35bf35,0xbf353f35,0x3f800000,0xbf80,0xbf800000,0x3f80,0x3f35bf35,0xbf35bf35,0xbf353f35,0x3f353f35,
0x80003f80,0x3f800000,0x80003f80,0x3f800000,0x3f800000,0xbf80,0x3f800000,0xbf80,0x8000bf80,0xbf800000,0x8000bf80,0xbf800000,
0xbf800000,0x3f80,0xbf800000,0x3f80,0x80003f80,0x3f800000,0x8000bf80,0xbf800000,0x3f35bf35,0xbf35bf35,0xbf353f35,0x3f353f35,
0xbf800000,0x3f80,0x3f800000,0xbf80,0x3f353f35,0x3f35bf35,0xbf35bf35,0xbf353f35,0x80003f80,0x3f800000,0x80003f80,0x3f800000,
0x8000bf80,0xbf800000,0x8000bf80,0xbf800000,0x80003f80,0x3f800000,0x80003f80,0x3f800000,0x8000bf80,0xbf800000,0x8000bf80,0xbf800000,
0x80003f80,0x3f800000,0x8000bf80,0xbf800000,0xbf35bf35,0xbf353f35,0x3f353f35,0x3f35bf35,0x3f800000,0xbf80,0xbf800000,0x3f80,
0xbf353f35,0x3f353f35,0x3f35bf35,0xbf35bf35,0x80003f80,0x3f800000,0x80003f80,0x3f800000,0xbf800000,0x3f80,0xbf800000,0x3f80,
0x8000bf80,0xbf800000,0x8000bf80,0xbf800000,0x3f800000,0xbf80,0x3f800000,0xbf80,0x80003f80,0x3f800000,0x8000bf80,0xbf800000,
0xbf353f35,0x3f353f35,0x3f35bf35,0xbf35bf35,0xbf800000,0x3f80,0x3f800000,0xbf80,0xbf35bf35,0xbf353f35,0x3f353f35,0x3f35bf35,
0x3f803f80,0x80008000,0x80008000,0xbf80bf80,0x3f803f80,0x80008000,0x80008000,0xbf80bf80,0x3f803f80,0x80008000,0x80008000,0xbf80bf80,
0x3f803f80,0x80008000,0x80008000,0xbf80bf80,0x3f353f80,0x3f358000,0x3f358000,0xbf35bf80,0xbf350000,0x3f353f80,0x3f353f80,0x3f358000,
0xbf35bf80,0xbf358000,0xbf358000,0x3f353f80,0x3f350000,0xbf35bf80,0xbf35bf80,0xbf358000,0x3f80,0x3f808000,0x3f808000,0x8000bf80,
0xbf80,0xbf808000,0xbf808000,0x80003f80,0x3f80,0x3f808000,0x3f808000,0x8000bf80,0xbf80,0xbf808000,0xbf808000,0x80003f80,
0xbf353f80,0x3f358000,0x3f358000,0x3f35bf80,0x3f350000,0x3f35bf80,0x3f35bf80,0xbf358000,0x3f35bf80,0xbf358000,0xbf358000,0xbf353f80,
0xbf350000,0xbf353f80,0xbf353f80,0x3f358000,0xbf803f80,0x80008000,0x80008000,0x3f80bf80,0xbf803f80,0x80008000,0x80008000,0x3f80bf80,
0xbf803f80,0x80008000,0x80008000,0x3f80bf80,0xbf803f80,0x80008000,0x80008000,0x3f80bf80,0xbf353f80,0xbf358000,0xbf358000,0x3f35bf80,
0x3f350000,0xbf353f80,0xbf353f80,0xbf358000,0x3f35bf80,0x3f358000,0x3f358000,0xbf353f80,0xbf350000,0x3f35bf80,0x3f35bf80,0x3f358000,
0x3f80,0xbf808000,0xbf808000,0x8000bf80,0xbf80,0x3f808000,0x3f808000,0x80003f80,0x3f80,0xbf808000,0xbf808000,0x8000bf80,
0xbf80,0x3f808000,0x3f808000,0x80003f80,0x3f353f80,0xbf358000,0xbf358000,0xbf35bf80,0xbf350000,0xbf35bf80,0xbf35bf80,0x3f358000,
0xbf35bf80,0x3f358000,0x3f358000,0x3f353f80,0x3f350000,0x3f353f80,0x3f353f80,0xbf358000,0x3f800000,0x0,0x3f800000,0x0,
0x3f800000,0x0,0x3f800000,0x0,0x3f800000,0x0,0x3f800000,0x0,0x3f800000,0x0,0x3f800000,0x0,
0x3f800000,0x0,0x3f7fb10f,0xbd48fb30,0x3f7ec46d,0xbdc8bd36,0x3f7d3aac,0xbe164083,0x3f7b14be,0xbe47c5c2,0x3f7853f8,0xbe78cfcc,
0x3f74fa0b,0xbe94a031,0x3f710908,0xbeac7cd4,0x3f800000,0x0,0x3f7ec46d,0xbdc8bd36,0x3f7b14be,0xbe47c5c2,0x3f74fa0b,0xbe94a031,
0x3f6c835e,0xbec3ef15,0x3f61c598,0xbef15aea,0x3f54db31,0xbf0e39da,0x3f45e403,0xbf226799,0x3f800000,0x0,0x3f7d3aac,0xbe164083,
0x3f74fa0b,0xbe94a031,0x3f676bd8,0xbedae880,0x3f54db31,0xbf0e39da,0x3f3daef9,0xbf2beb4a,0x3f226799,0xbf45e403,0x3f039c3d,0xbf5b941a,
0x3f800000,0x0,0x3f7b14be,0xbe47c5c2,0x3f6c835e,0xbec3ef15,0x3f54db31,0xbf0e39da,0x3f3504f3,0xbf3504f3,0x3f0e39da,0xbf54db31,
0x3ec3ef15,0xbf6c835e,0x3e47c5c2,0xbf7b14be,0x3f800000,0x0,0x3f7853f8,0xbe78cfcc,0x3f61c598,0xbef15aea,0x3f3daef9,0xbf2beb4a,
0x3f0e39da,0xbf54db31,0x3eac7cd4,0xbf710908,0x3dc8bd36,0xbf7ec46d,0xbe164083,0xbf7d3aac,0x3f800000,0x0,0x3f74fa0b,0xbe94a031,
0x3f54db31,0xbf0e39da,0x3f226799,0xbf45e403,0x3ec3ef15,0xbf6c835e,0x3dc8bd36,0xbf7ec46d,0xbe47c5c2,0xbf7b14be,0xbef15aea,0xbf61c598,
0x3f800000,0x0,0x3f710908,0xbeac7cd4,0x3f45e403,0xbf226799,0x3f039c3d,0xbf5b941a,0x3e47c5c2,0xbf7b14be,0xbe164083,0xbf7d3aac,
0xbef15aea,0xbf61c598,0xbf3daef9,0xbf2beb4a,0x3f800000,0x0,0x3f800000,0x0,0x3f800000,0x0,0x3f800000,0x0,
0x3f800000,0x0,0x3f800000,0x0,0x3f800000,0x0,0x3f800000,0x0,0x3f6c835e,0xbec3ef15,0x3f676bd8,0xbedae880,
0x3f61c598,0xbef15aea,0x3f5b941a,0xbf039c3d,0x3f54db31,0xbf0e39da,0x3f4d9f02,0xbf187fc0,0x3f45e403,0xbf226799,0x3f3daef9,0xbf2beb4a,
0x3f3504f3,0xbf3504f3,0x3f226799,0xbf45e403,0x3f0e39da,0xbf54db31,0x3ef15aea,0xbf61c598,0x3ec3ef15,0xbf6c835e,0x3e94a031,0xbf74fa0b,
0x3e47c5c2,0xbf7b14be,0x3dc8bd36,0xbf7ec46d,0x3ec3ef15,0xbf6c835e,0x3e78cfcc,0xbf7853f8,0x3dc8bd36,0xbf7ec46d,0xbd48fb30,0xbf7fb10f,
0xbe47c5c2,0xbf7b14be,0xbeac7cd4,0xbf710908,0xbef15aea,0xbf61c598,0xbf187fc0,0xbf4d9f02,0x0,0xbf800000,0xbe47c5c2,0xbf7b14be,
0xbec3ef15,0xbf6c835e,0xbf0e39da,0xbf54db31,0xbf3504f3,0xbf3504f3,0xbf54db31,0xbf0e39da,0xbf6c835e,0xbec3ef15,0xbf7b14be,0xbe47c5c2,
0xbec3ef15,0xbf6c835e,0xbf187fc0,0xbf4d9f02,0xbf45e403,0xbf226799,0xbf676bd8,0xbedae880,0xbf7b14be,0xbe47c5c2,0xbf7fb10f,0x3d48fb30,
0xbf74fa0b,0x3e94a031,0xbf5b941a,0x3f039c3d,0xbf3504f3,0xbf3504f3,0xbf61c598,0xbef15aea,0xbf7b14be,0xbe47c5c2,0xbf7ec46d,0x3dc8bd36,
0xbf6c835e,0x3ec3ef15,0xbf45e403,0x3f226799,0xbf0e39da,0x3f54db31,0xbe94a031,0x3f74fa0b,0xbf6c835e,0xbec3ef15,0xbf7fb10f,0xbd48fb30,
0xbf74fa0b,0x3e94a031,0xbf4d9f02,0x3f187fc0,0xbf0e39da,0x3f54db31,0xbe78cfcc,0x3f7853f8,0x3dc8bd36,0x3f7ec46d,0x3edae880,0x3f676bd8,
0x80003f80,0x3f800000,0x3f800000,0xbf80,0x3ec43f6d,0x3f6dbec4,0x3f6dbec4,0xbec4bf6d,0x3f353f35,0x3f35bf35,0x3f35bf35,0xbf35bf35,
0x3f6d3ec4,0x3ec4bf6d,0x3ec4bf6d,0xbf6dbec4,0x80003f80,0x3f800000,0xbf800000,0x3f80,0x3f6d3ec4,0x3ec4bf6d,0xbec43f6d,0x3f6d3ec4,
0x3f35bf35,0xbf35bf35,0x3f353f35,0x3f35bf35,0xbec4bf6d,0xbf6d3ec4,0x3f6dbec4,0xbec4bf6d,0x80003f80,0x3f800000,0x3f800000,0xbf80,
0x3f6dbec4,0xbec4bf6d,0xbec4bf6d,0xbf6d3ec4,0xbf35bf35,0xbf353f35,0xbf353f35,0x3f353f35,0xbec43f6d,0x3f6d3ec4,0x3f6d3ec4,0x3ec4bf6d,
0x80003f80,0x3f800000,0xbf800000,0x3f80,0x3ec4bf6d,0xbf6dbec4,0x3f6d3ec4,0x3ec4bf6d,0xbf353f35,0x3f353f35,0xbf35bf35,0xbf353f35,
0x3f6dbec4,0xbec4bf6d,0x3ec43f6d,0x3f6dbec4,0x80003f80,0x3f800000,0x3f800000,0xbf80,0xbec4bf6d,0xbf6d3ec4,0xbf6d3ec4,0x3ec43f6d,
0x3f353f35,0x3f35bf35,0x3f35bf35,0xbf35bf35,0xbf6dbec4,0xbec43f6d,0xbec43f6d,0x3f6d3ec4,0x80003f80,0x3f800000,0xbf800000,0x3f80,
0xbf6dbec4,0xbec43f6d,0x3ec4bf6d,0xbf6dbec4,0x3f35bf35,0xbf35bf35,0x3f353f35,0x3f35bf35,0x3ec43f6d,0x3f6dbec4,0xbf6d3ec4,0x3ec43f6d,
0x80003f80,0x3f800000,0x3f800000,0xbf80,0xbf6d3ec4,0x3ec43f6d,0x3ec43f6d,0x3f6dbec4,0xbf35bf35,0xbf353f35,0xbf353f35,0x3f353f35,
0x3ec4bf6d,0xbf6dbec4,0xbf6dbec4,0xbec43f6d,0x80003f80,0x3f800000,0xbf800000,0x3f80,0xbec43f6d,0x3f6d3ec4,0xbf6dbec4,0xbec43f6d,
0xbf353f35,0x3f353f35,0xbf35bf35,0xbf353f35,0xbf6d3ec4,0x3ec43f6d,0xbec4bf6d,0xbf6d3ec4,0x3f803f80,0x80008000,0x80008000,0xbf80bf80,
0x3f803f80,0x80008000,0x80008000,0xbf80bf80,0x3f803f80,0x80008000,0x80008000,0xbf80bf80,0x3f803f80,0x80008000,0x80008000,0xbf80bf80,
0x3ec43f6d,0x3f6d3ec4,0x3f6d3ec4,0xbec4bf6d,0xbf6dbec4,0x3ec43f6d,0x3ec43f6d,0x3f6d3ec4,0xbec4bf6d,0xbf6dbec4,0xbf6dbec4,0x3ec43f6d,
0x3f6d3ec4,0xbec4bf6d,0xbec4bf6d,0xbf6dbec4,0xbf353f35,0x3f353f35,0x3f353f35,0x3f35bf35,0x3f35bf35,0xbf35bf35,0xbf35bf35,0xbf353f35,
0xbf353f35,0x3f353f35,0x3f353f35,0x3f35bf35,0x3f35bf35,0xbf35bf35,0xbf35bf35,0xbf353f35,0xbf6d3ec4,0xbec43f6d,0xbec43f6d,0x3f6dbec4,
0xbec43f6d,0x3f6dbec4,0x3f6dbec4,0x3ec4bf6d,0x3f6dbec4,0x3ec4bf6d,0x3ec4bf6d,0xbf6d3ec4,0x3ec4bf6d,0xbf6d3ec4,0xbf6d3ec4,0xbec43f6d,
0x0,0xbf803f80,0xbf803f80,0x80008000,0x0,0xbf803f80,0xbf803f80,0x80008000,0x0,0xbf803f80,0xbf803f80,0x80008000,
0x0,0xbf803f80,0xbf803f80,0x80008000,0x3f6dbec4,0xbec43f6d,0xbec43f6d,0xbf6d3ec4,0x3ec4bf6d,0x3f6dbec4,0x3f6dbec4,0xbec43f6d,
0xbf6d3ec4,0x3ec4bf6d,0x3ec4bf6d,0x3f6dbec4,0xbec43f6d,0xbf6d3ec4,0xbf6d3ec4,0x3ec4bf6d,0x3f35bf35,0x3f353f35,0x3f353f35,0xbf353f35,
0xbf353f35,0xbf35bf35,0xbf35bf35,0x3f35bf35,0x3f35bf35,0x3f353f35,0x3f353f35,0xbf353f35,0xbf353f35,0xbf35bf35,0xbf35bf35,0x3f35bf35,
0xbec4bf6d,0x3f6d3ec4,0x3f6d3ec4,0x3ec43f6d,0x3f6d3ec4,0x3ec43f6d,0x3ec43f6d,0xbf6dbec4,0x3ec43f6d,0xbf6dbec4,0xbf6dbec4,0xbec4bf6d,
0xbf6dbec4,0xbec4bf6d,0xbec4bf6d,0x3f6d3ec4,0x3f800000,0x0,0x3f7fec43,0xbcc90ab0,0x3f7fb10f,0xbd48fb30,0x3f7f4e6d,0xbd96a905,
0x3f7ec46d,0xbdc8bd36,0x3f7e1324,0xbdfab273,0x3f7d3aac,0xbe164083,0x3f7c3b28,0xbe2f10a2,0x3f800000,0x0,0x3f7f4e6d,0xbd96a905,
0x3f7d3aac,0xbe164083,0x3f79c79d,0xbe605c13,0x3f74fa0b,0xbe94a031,0x3f6ed89e,0xbeb8442a,0x3f676bd8,0xbedae880,0x3f5ebe05,0xbefc5d27,
0x3f800000,0x0,0x3f7e1324,0xbdfab273,0x3f7853f8,0xbe78cfcc,0x3f6ed89e,0xbeb8442a,0x3f61c598,0xbef15aea,0x3f514d3d,0xbf13682a,
0x3f3daef9,0xbf2beb4a,0x3f273656,0xbf41d870,0x3f800000,0x0,0x3f7c3b28,0xbe2f10a2,0x3f710908,0xbeac7cd4,0x3f5ebe05,0xbefc5d27,
0x3f45e403,0xbf226799,0x3f273656,0xbf41d870,0x3f039c3d,0xbf5b941a,0x3eb8442a,0xbf6ed89e,0x3f800000,0x0,0x3f79c79d,0xbe605c13,
0x3f676bd8,0xbedae880,0x3f49d112,0xbf1d7fd1,0x3f226799,0xbf45e403,0x3ee63375,0xbf64aa59,0x3e78cfcc,0xbf7853f8,0x3cc90ab0,0xbf7fec43,
0x3f800000,0x0,0x3f76ba07,0xbe888e93,0x3f5b941a,0xbf039c3d,0x3f3085bb,0xbf396842,0x3ef15aea,0xbf61c598,0x3e605c13,0xbf79c79d,
0xbd48fb30,0xbf7fb10f,0xbea09ae5,0xbf731447,0x3f800000,0x0,0x3f731447,0xbea09ae5,0x3f4d9f02,0xbf187fc0,0x3f13682a,0xbf514d3d,
0x3e94a031,0xbf74fa0b,0xbcc90ab0,0xbf7fec43,0xbeac7cd4,0xbf710908,0xbf1d7fd1,0xbf49d112,0x3f800000,0x0,0x3f6ed89e,0xbeb8442a,
0x3f3daef9,0xbf2beb4a,0x3ee63375,0xbf64aa59,0x3dc8bd36,0xbf7ec46d,0xbe888e93,0xbf76ba07,0xbf187fc0,0xbf4d9f02,0xbf584853,0xbf08f59b,
0x3f7b14be,0xbe47c5c2,0x3f79c79d,0xbe605c13,0x3f7853f8,0xbe78cfcc,0x3f76ba07,0xbe888e93,0x3f74fa0b,0xbe94a031,0x3f731447,0xbea09ae5,
0x3f710908,0xbeac7cd4,0x3f6ed89e,0xbeb8442a,0x3f54db31,0xbf0e39da,0x3f49d112,0xbf1d7fd1,0x3f3daef9,0xbf2beb4a,0x3f3085bb,0xbf396842,
0x3f226799,0xbf45e403,0x3f13682a,0xbf514d3d,0x3f039c3d,0xbf5b941a,0x3ee63375,0xbf64aa59,0x3f0e39da,0xbf54db31,0x3ee63375,0xbf64aa59,
0x3eac7cd4,0xbf710908,0x3e605c13,0xbf79c79d,0x3dc8bd36,0xbf7ec46d,0xbcc90ab0,0xbf7fec43,0xbe164083,0xbf7d3aac,0xbe888e93,0xbf76ba07,
0x3e47c5c2,0xbf7b14be,0x3cc90ab0,0xbf7fec43,0xbe164083,0xbf7d3aac,0xbea09ae5,0xbf731447,0xbef15aea,0xbf61c598,0xbf1d7fd1,0xbf49d112,
0xbf3daef9,0xbf2beb4a,0xbf584853,0xbf08f59b,0xbe47c5c2,0xbf7b14be,0xbecf7bca,0xbf6a09a7,0xbf187fc0,0xbf4d9f02,0xbf41d870,0xbf273656,
0xbf61c598,0xbef15aea,0xbf76ba07,0xbe888e93,0xbf7fb10f,0xbd48fb30,0xbf7c3b28,0x3e2f10a2,0xbf0e39da,0xbf54db31,0xbf41d870,0xbf273656,
0xbf676bd8,0xbedae880,0xbf7c3b28,0xbe2f10a2,0xbf7ec46d,0x3dc8bd36,0xbf6ed89e,0x3eb8442a,0xbf4d9f02,0x3f187fc0,0xbf1d7fd1,0x3f49d112,
0xbf54db31,0xbf0e39da,0xbf76ba07,0xbe888e93,0xbf7fb10f,0x3d48fb30,0xbf6ed89e,0x3eb8442a,0xbf45e403,0x3f226799,0xbf08f59b,0x3f584853,
0xbe78cfcc,0x3f7853f8,0x3d96a905,0x3f7f4e6d,0xbf7b14be,0xbe47c5c2,0xbf7c3b28,0x3e2f10a2,0xbf5b941a,0x3f039c3d,0xbf1d7fd1,0x3f49d112,
0xbe94a031,0x3f74fa0b,0x3d96a905,0x3f7f4e6d,0x3edae880,0x3f676bd8,0x3f396842,0x3f3085bb,0x80003f80,0x80003f80,0x80003f80,0x80003f80,
0x80003f80,0x80003f80,0x80003f80,0x80003f80,0x80003f80,0x80003f80,0x80003f80,0x80003f80,0x80003f80,0x80003f80,0x80003f80,0x80003f80,
0x3f800000,0x3f800000,0x3f800000,0x3f800000,0x3f800000,0x3f800000,0x3f800000,0x3f800000,0x3f800000,0x3f800000,0x3f800000,0x3f800000,
0x3f800000,0x3f800000,0x3f800000,0x3f800000,0x80003f80,0x3f353f35,0x80003f80,0x3f353f35,0x3f800000,0x3f35bf35,0x3f800000,0x3f35bf35,
0x8000bf80,0xbf35bf35,0x8000bf80,0xbf35bf35,0xbf800000,0xbf353f35,0xbf800000,0xbf353f35,0x3f800000,0x3f35bf35,0x3f800000,0x3f35bf35,
0xbf80,0xbf35bf35,0xbf80,0xbf35bf35,0xbf800000,0xbf353f35,0xbf800000,0xbf353f35,0x3f80,0x3f353f35,0x3f80,0x3f353f35,
0x80003f80,0x3f800000,0x80003f80,0x3f800000,0x8000bf80,0xbf800000,0x8000bf80,0xbf800000,0x80003f80,0x3f800000,0x80003f80,0x3f800000,
0x8000bf80,0xbf800000,0x8000bf80,0xbf800000,0x3f800000,0xbf80,0x3f800000,0xbf80,0xbf800000,0x3f80,0xbf800000,0x3f80,
0x3f800000,0xbf80,0x3f800000,0xbf80,0xbf800000,0x3f80,0xbf800000,0x3f80,0x80003f80,0x3f35bf35,0x80003f80,0x3f35bf35,
0xbf800000,0x3f353f35,0xbf800000,0x3f353f35,0x8000bf80,0xbf353f35,0x8000bf80,0xbf353f35,0x3f800000,0xbf35bf35,0x3f800000,0xbf35bf35,
0x3f800000,0xbf35bf35,0x3f800000,0xbf35bf35,0x3f80,0x3f35bf35,0x3f80,0x3f35bf35,0xbf800000,0x3f353f35,0xbf800000,0x3f353f35,
0xbf80,0xbf353f35,0xbf80,0xbf353f35,0x80003f80,0x3ec43f6d,0x8000bf80,0xbec4bf6d,0x3f353f35,0x3f6d3ec4,0xbf35bf35,0xbf6dbec4,
0x3f800000,0x3f6dbec4,0xbf800000,0xbf6d3ec4,0x3f35bf35,0x3ec4bf6d,0xbf353f35,0xbec43f6d,0x3f800000,0x3f6dbec4,0xbf800000,0xbf6d3ec4,
0x3f35bf35,0x3ec4bf6d,0xbf353f35,0xbec43f6d,0xbf80,0xbec4bf6d,0x3f80,0x3ec43f6d,0xbf35bf35,0xbf6dbec4,0x3f353f35,0x3f6d3ec4,
0x80003f80,0x3f6d3ec4,0x8000bf80,0xbf6dbec4,0x3f35bf35,0xbec4bf6d,0xbf353f35,0x3ec43f6d,0xbf800000,0xbec43f6d,0x3f800000,0x3ec4bf6d,
0x3f353f35,0x3f6dbec4,0xbf35bf35,0xbf6d3ec4,0x3f800000,0x3ec4bf6d,0xbf800000,0xbec43f6d,0xbf35bf35,0xbf6d3ec4,0x3f353f35,0x3f6dbec4,
0x3f80,0x3f6d3ec4,0xbf80,0xbf6dbec4,0x3f35bf35,0xbec4bf6d,0xbf353f35,0x3ec43f6d,0x80003f80,0x3f6dbec4,0x8000bf80,0xbf6d3ec4,
0xbf35bf35,0xbec43f6d,0x3f353f35,0x3ec4bf6d,0x3f800000,0xbec4bf6d,0xbf800000,0x3ec43f6d,0xbf353f35,0x3f6d3ec4,0x3f35bf35,0xbf6dbec4,
0x3f800000,0xbec4bf6d,0xbf800000,0x3ec43f6d,0xbf353f35,0x3f6d3ec4,0x3f35bf35,0xbf6dbec4,0xbf80,0xbf6d3ec4,0x3f80,0x3f6dbec4,
0x3f353f35,0x3ec4bf6d,0xbf35bf35,0xbec43f6d,0x80003f80,0x3ec4bf6d,0x8000bf80,0xbec43f6d,0xbf353f35,0x3f6dbec4,0x3f35bf35,0xbf6d3ec4,
0xbf800000,0x3f6d3ec4,0x3f800000,0xbf6dbec4,0xbf35bf35,0x3ec43f6d,0x3f353f35,0xbec4bf6d,0x3f800000,0xbf6dbec4,0xbf800000,0x3f6d3ec4,
0x3f353f35,0xbec4bf6d,0xbf35bf35,0x3ec43f6d,0x3f80,0x3ec4bf6d,0xbf80,0xbec43f6d,0xbf353f35,0x3f6dbec4,0x3f35bf35,0xbf6d3ec4,
0x80003f80,0x8000bf80,0x80003f80,0x8000bf80,0x80003f80,0x8000bf80,0x80003f80,0x8000bf80,0x80003f80,0x8000bf80,0x80003f80,0x8000bf80,
0x80003f80,0x8000bf80,0x80003f80,0x8000bf80,0x3f800000,0xbf800000,0x3f800000,0xbf800000,0x3f800000,0xbf800000,0x3f800000,0xbf800000,
0x3f800000,0xbf800000,0x3f800000,0xbf800000,0x3f800000,0xbf800000,0x3f800000,0xbf800000,0x80003f80,0xbf35bf35,0x80003f80,0xbf35bf35,
0x3f800000,0xbf353f35,0x3f800000,0xbf353f35,0x8000bf80,0x3f353f35,0x8000bf80,0x3f353f35,0xbf800000,0x3f35bf35,0xbf800000,0x3f35bf35,
0x3f800000,0xbf353f35,0x3f800000,0xbf353f35,0xbf80,0x3f353f35,0xbf80,0x3f353f35,0xbf800000,0x3f35bf35,0xbf800000,0x3f35bf35,
0x3f80,0xbf35bf35,0x3f80,0xbf35bf35,0x80003f80,0xbf800000,0x80003f80,0xbf800000,0x8000bf80,0x3f800000,0x8000bf80,0x3f800000,
0x80003f80,0xbf800000,0x80003f80,0xbf800000,0x8000bf80,0x3f800000,0x8000bf80,0x3f800000,0x3f800000,0x3f80,0x3f800000,0x3f80,
0xbf800000,0xbf80,0xbf800000,0xbf80,0x3f800000,0x3f80,0x3f800000,0x3f80,0xbf800000,0xbf80,0xbf800000,0xbf80,
0x80003f80,0xbf353f35,0x80003f80,0xbf353f35,0xbf800000,0xbf35bf35,0xbf800000,0xbf35bf35,0x8000bf80,0x3f35bf35,0x8000bf80,0x3f35bf35,
0x3f800000,0x3f353f35,0x3f800000,0x3f353f35,0x3f800000,0x3f353f35,0x3f800000,0x3f353f35,0x3f80,0xbf353f35,0x3f80,0xbf353f35,
0xbf800000,0xbf35bf35,0xbf800000,0xbf35bf35,0xbf80,0x3f35bf35,0xbf80,0x3f35bf35,0x80003f80,0xbec4bf6d,0x8000bf80,0x3ec43f6d,
0x3f353f35,0xbf6dbec4,0xbf35bf35,0x3f6d3ec4,0x3f800000,0xbf6d3ec4,0xbf800000,0x3f6dbec4,0x3f35bf35,0xbec43f6d,0xbf353f35,0x3ec4bf6d,
0x3f800000,0xbf6d3ec4,0xbf800000,0x3f6dbec4,0x3f35bf35,0xbec43f6d,0xbf353f35,0x3ec4bf6d,0xbf80,0x3ec43f6d,0x3f80,0xbec4bf6d,
0xbf35bf35,0x3f6d3ec4,0x3f353f35,0xbf6dbec4,0x80003f80,0xbf6dbec4,0x8000bf80,0x3f6d3ec4,0x3f35bf35,0x3ec43f6d,0xbf353f35,0xbec4bf6d,
0xbf800000,0x3ec4bf6d,0x3f800000,0xbec43f6d,0x3f353f35,0xbf6d3ec4,0xbf35bf35,0x3f6dbec4,0x3f800000,0xbec43f6d,0xbf800000,0x3ec4bf6d,
0xbf35bf35,0x3f6dbec4,0x3f353f35,0xbf6d3ec4,0x3f80,0xbf6dbec4,0xbf80,0x3f6d3ec4,0x3f35bf35,0x3ec43f6d,0xbf353f35,0xbec4bf6d,
0x80003f80,0xbf6d3ec4,0x8000bf80,0x3f6dbec4,0xbf35bf35,0x3ec4bf6d,0x3f353f35,0xbec43f6d,0x3f800000,0x3ec43f6d,0xbf800000,0xbec4bf6d,
0xbf353f35,0xbf6dbec4,0x3f35bf35,0x3f6d3ec4,0x3f800000,0x3ec43f6d,0xbf800000,0xbec4bf6d,0xbf353f35,0xbf6dbec4,0x3f35bf35,0x3f6d3ec4,
0xbf80,0x3f6dbec4,0x3f80,0xbf6d3ec4,0x3f353f35,0xbec43f6d,0xbf35bf35,0x3ec4bf6d,0x80003f80,0xbec43f6d,0x8000bf80,0x3ec4bf6d,
0xbf353f35,0xbf6d3ec4,0x3f35bf35,0x3f6dbec4,0xbf800000,0xbf6dbec4,0x3f800000,0x3f6d3ec4,0xbf35bf35,0xbec4bf6d,0x3f353f35,0x3ec43f6d,
0x3f800000,0x3f6d3ec4,0xbf800000,0xbf6dbec4,0x3f353f35,0x3ec43f6d,0xbf35bf35,0xbec4bf6d,0x3f80,0xbec43f6d,0xbf80,0x3ec4bf6d,
0xbf353f35,0xbf6d3ec4,0x3f35bf35,0x3f6dbec4,
};
constexpr int TB_F = 0, TB_E = 512, TB_P2 = 1024;

enum { C_EP = 0, C_Z1 = 32, C_Z2 = 96, C_H3 = 128, C_U = 160, C_X = 288, C_TOTAL = 512 };
struct Scratch {
  unsigned cnt[C_TOTAL];
  uint32_t moda[8 * 2 * D_];
  uint32_t mod[4 * D_ + 256];
  uint32_t z1[120 * 5120];
  uint32_t z2[128 * 4800];
  uint8_t h3[32 * 18 * 4096];
  uint8_t u[72 * D_ * 128];
};
__device__ __align__(1024) Scratch g_s;

constexpr int HOLDA = 5;
constexpr int X1K = 10;
constexpr int NV1 = 12;
constexpr int NV2 = 20;
constexpr int W0N = 3;
constexpr int TRK0 = 50;
constexpr int TRKC = 350;
constexpr int HD1 = 150;
constexpr int EH = 7;

struct Maps { CUtensorMap z1, z2[2], w1a, w1b, h3, w2, wf[4], wm; };
struct Params {
  const __nv_bfloat16 *x, *c, *wmod;
  Scratch* s;
  const uint4* tab;
  const __nv_bfloat16 *wr, *wi, *w1, *w2, *b1, *b2;
  uint32_t* out;
};

__device__ __forceinline__ uint32_t smem_u32(const void* p) { return (uint32_t)__cvta_generic_to_shared(p); }
__device__ __forceinline__ void mbar_init(uint32_t b, int c) { asm volatile("mbarrier.init.shared::cta.b64 [%0], %1;" ::"r"(b), "r"(c)); }
__device__ __forceinline__ void mbar_expect(uint32_t b, int bytes) { asm volatile("mbarrier.arrive.expect_tx.shared::cta.b64 _, [%0], %1;" ::"r"(b), "r"(bytes) : "memory"); }
__device__ __forceinline__ void mbar_arrive(uint32_t b) { asm volatile("mbarrier.arrive.shared::cta.b64 _, [%0];" ::"r"(b) : "memory"); }
__device__ __forceinline__ void mbar_wait(uint32_t b, int ph) {
  asm volatile("{\n.reg .pred p;\n.reg .u32 it;\nmov.u32 it, 0;\nW:\nmbarrier.try_wait.parity.shared::cta.b64 p, [%0], %1;\n"
               "@p bra.uni D;\nadd.u32 it, it, 1;\nsetp.lt.u32 p, it, 0x400000;\n@p bra.uni W;\ntrap;\nD:\n}" ::"r"(b), "r"(ph) : "memory");
}
__device__ __forceinline__ uint32_t mbar_test(uint32_t b, int ph) {
  uint32_t ok;
  asm volatile("{\n.reg .pred p;\nmbarrier.test_wait.parity.shared::cta.b64 p, [%1], %2;\nselp.u32 %0, 1, 0, p;\n}\n" : "=r"(ok) : "r"(b), "r"(ph) : "memory");
  return ok;
}
__device__ __forceinline__ void tma2d(uint32_t dst, const CUtensorMap* m, int c0, int c1, uint32_t bar) {
  asm volatile("cp.async.bulk.tensor.2d.shared::cluster.global.mbarrier::complete_tx::bytes [%0], [%1, {%3, %4}], [%2];" ::"r"(dst), "l"(m), "r"(bar), "r"(c0), "r"(c1) : "memory");
}
__device__ __forceinline__ uint64_t pol_ef() { uint64_t p; asm("createpolicy.fractional.L2::evict_first.b64 %0, 1.0;" : "=l"(p)); return p; }
__device__ __forceinline__ void tma3d_ef(uint32_t dst, const CUtensorMap* m, int c1, int c2, uint32_t bar) {
  asm volatile("cp.async.bulk.tensor.3d.shared::cluster.global.mbarrier::complete_tx::bytes.L2::cache_hint [%0], [%1, {%3, %4, %5}], [%2], %6;" ::"r"(dst), "l"(m), "r"(bar), "r"(0), "r"(c1), "r"(c2), "l"(pol_ef()) : "memory");
}
__device__ __forceinline__ void tma4d_ef(uint32_t dst, const CUtensorMap* m, int c1, int c2, int c3, uint32_t bar) {
  asm volatile("cp.async.bulk.tensor.4d.shared::cluster.global.mbarrier::complete_tx::bytes.L2::cache_hint [%0], [%1, {%3, %7, %4, %5}], [%2], %6;" ::"r"(dst), "l"(m), "r"(bar), "r"(0), "r"(c2), "r"(c3), "l"(pol_ef()), "r"(c1) : "memory");
}
__device__ __forceinline__ void bulk_ld(uint32_t dst, const void* src, int bytes, uint32_t bar) {
  asm volatile("cp.async.bulk.shared::cluster.global.mbarrier::complete_tx::bytes [%0], [%1], %2, [%3];" ::"r"(dst), "l"(src), "r"(bytes), "r"(bar) : "memory");
}
__device__ __forceinline__ void bulk_st(void* dst, uint32_t src, int bytes) {
  asm volatile("cp.async.bulk.global.shared::cta.bulk_group [%0], [%1], %2;" ::"l"(dst), "r"(src), "r"(bytes) : "memory");
}
__device__ __forceinline__ void tma_st2d(const CUtensorMap* m, uint32_t src, int c0, int c1) {
  asm volatile("cp.async.bulk.tensor.2d.global.shared::cta.bulk_group [%0, {%2, %3}], [%1];" ::"l"(m), "r"(src), "r"(c0), "r"(c1) : "memory");
}
__device__ __forceinline__ void tma_st3d(const CUtensorMap* m, uint32_t src, int c0, int c1, int c2) {
  asm volatile("cp.async.bulk.tensor.3d.global.shared::cta.bulk_group [%0, {%2, %3, %4}], [%1];" ::"l"(m), "r"(src), "r"(c0), "r"(c1), "r"(c2) : "memory");
}
__device__ __forceinline__ void bulk_commit_wait() {
  asm volatile("cp.async.bulk.commit_group;" ::: "memory");
  asm volatile("cp.async.bulk.wait_group 0;" ::: "memory");
}
__device__ __forceinline__ void prefetch_l2(const void* p, int bytes) {
  asm volatile("cp.async.bulk.prefetch.L2.global [%0], %1;" ::"l"(p), "r"(bytes) : "memory");
}
__device__ __forceinline__ void wg_fence() { asm volatile("wgmma.fence.sync.aligned;" ::: "memory"); }
__device__ __forceinline__ void wg_commit() { asm volatile("wgmma.commit_group.sync.aligned;" ::: "memory"); }
template <int N> __device__ __forceinline__ void wg_wait() { asm volatile("wgmma.wait_group.sync.aligned %0;" ::"n"(N) : "memory"); }
template <int N> __device__ __forceinline__ void reg_fence(float (&d)[N]) {
#pragma unroll
  for (int i = 0; i < N; i++) asm volatile("" : "+f"(d[i])::"memory");
}
__device__ __forceinline__ void fence_async_smem() { asm volatile("fence.proxy.async.shared::cta;" ::: "memory"); }
__device__ __forceinline__ void fence_async_glb() { asm volatile("fence.proxy.async.global;" ::: "memory"); }
__device__ __forceinline__ uint32_t ld_rlx(const void* p) { uint32_t v; asm volatile("ld.relaxed.gpu.global.b32 %0, [%1];" : "=r"(v) : "l"(p) : "memory"); return v; }
__device__ __forceinline__ uint2 ld_rlx2(const void* p) { uint2 v; asm volatile("ld.relaxed.gpu.global.v2.b32 {%0,%1}, [%2];" : "=r"(v.x), "=r"(v.y) : "l"(p) : "memory"); return v; }
__device__ __forceinline__ uint4 ld_rlx4(const void* p) { uint4 v; asm volatile("ld.relaxed.gpu.global.v4.b32 {%0,%1,%2,%3}, [%4];" : "=r"(v.x), "=r"(v.y), "=r"(v.z), "=r"(v.w) : "l"(p) : "memory"); return v; }
__device__ __forceinline__ uint32_t ld_nc(const void* p) { uint32_t v; asm volatile("ld.global.nc.L1::no_allocate.b32 %0, [%1];" : "=r"(v) : "l"(p) : "memory"); return v; }
__device__ __forceinline__ uint4 ld_nc4(const void* p) { uint4 v; asm volatile("ld.global.nc.v4.b32 {%0,%1,%2,%3}, [%4];" : "=r"(v.x), "=r"(v.y), "=r"(v.z), "=r"(v.w) : "l"(p) : "memory"); return v; }
__device__ __forceinline__ uint32_t lds(uint32_t a) { uint32_t v; asm volatile("ld.shared.b32 %0, [%1];" : "=r"(v) : "r"(a) : "memory"); return v; }
__device__ __forceinline__ uint2 lds2(uint32_t a) { uint2 v; asm volatile("ld.shared.v2.b32 {%0,%1}, [%2];" : "=r"(v.x), "=r"(v.y) : "r"(a) : "memory"); return v; }
__device__ __forceinline__ void lds2_if(int on, uint2& v, uint32_t a) { asm volatile("{\n.reg .pred p;\nsetp.ne.u32 p, %3, 0;\n@p ld.shared.v2.b32 {%0,%1}, [%2];\n}" : "+r"(v.x), "+r"(v.y) : "r"(a), "r"(on) : "memory"); }
__device__ __forceinline__ uint4 lds4(uint32_t a) { uint4 v; asm volatile("ld.shared.v4.b32 {%0,%1,%2,%3}, [%4];" : "=r"(v.x), "=r"(v.y), "=r"(v.z), "=r"(v.w) : "r"(a) : "memory"); return v; }
__device__ __forceinline__ float lds_bf(uint32_t a) { uint32_t v; asm volatile("ld.shared.u16 %0, [%1];" : "=r"(v) : "r"(a) : "memory"); return __uint_as_float(v << 16); }
__device__ __forceinline__ void sts(uint32_t a, uint32_t v) { asm volatile("st.shared.b32 [%0], %1;" ::"r"(a), "r"(v) : "memory"); }
__device__ __forceinline__ void sts2(uint32_t a, uint32_t v0, uint32_t v1) { asm volatile("st.shared.v2.b32 [%0], {%1,%2};" ::"r"(a), "r"(v0), "r"(v1) : "memory"); }
__device__ __forceinline__ void sts4(uint32_t a, uint32_t v0, uint32_t v1, uint32_t v2, uint32_t v3) { asm volatile("st.shared.v4.b32 [%0], {%1,%2,%3,%4};" ::"r"(a), "r"(v0), "r"(v1), "r"(v2), "r"(v3) : "memory"); }
__device__ __forceinline__ void bar_sync(int id, int n) { asm volatile("bar.sync %0, %1;" ::"r"(id), "r"(n) : "memory"); }
__device__ __forceinline__ void bar_arrive(int id, int n) { asm volatile("bar.arrive %0, %1;" ::"r"(id), "r"(n) : "memory"); }
__device__ __forceinline__ void red_add(unsigned* p, unsigned v) { asm volatile("red.relaxed.gpu.global.add.u32 [%0], %1;" ::"l"(p), "r"(v) : "memory"); }
__device__ __forceinline__ bool any(bool p) { return __any_sync(0xffffffffu, p); }
__device__ __forceinline__ void pause(unsigned clks) {
  asm volatile("{\n.reg .pred p;\n.reg .u32 a, b;\nmov.u32 a, %%clock;\nW:\nmov.u32 b, %%clock;\nsub.u32 b, b, a;\nsetp.lt.s32 p, b, %0;\n@p bra.uni W;\n}" ::"r"(clks) : "memory");
}
__device__ __forceinline__ void red_bf16x8(uint32_t* p, uint32_t a, uint32_t b, uint32_t c, uint32_t d) {
  asm volatile("red.relaxed.gpu.global.add.noftz.v4.bf16x2 [%0], {%1,%2,%3,%4};" ::"l"(p), "r"(a), "r"(b), "r"(c), "r"(d) : "memory");
}
__device__ __forceinline__ void red_bf16x4(uint32_t* p, uint32_t a, uint32_t b) {
  asm volatile("red.relaxed.gpu.global.add.noftz.v2.bf16x2 [%0], {%1,%2};" ::"l"(p), "r"(a), "r"(b) : "memory");
}
constexpr int SPIN_MAX = 1 << 20;
__device__ __forceinline__ uint32_t ld_acq(const void* p) { uint32_t v; asm volatile("ld.acquire.gpu.global.b32 %0, [%1];" : "=r"(v) : "l"(p) : "memory"); return v; }
template <bool ACQ = false> __device__ __forceinline__ void wait_cnt(const unsigned* p, unsigned target) {
  int it = 0;
  while (any((int)((ACQ ? ld_acq(p) : ld_rlx(p)) - target) < 0) && ++it < SPIN_MAX) {}
}
__device__ __forceinline__ uint32_t pack_bf16(float lo, float hi) { uint32_t r; asm("cvt.rn.bf16x2.f32 %0, %1, %2;" : "=r"(r) : "f"(hi), "f"(lo)); return r; }
__device__ __forceinline__ float bf_lo(uint32_t v) { return __uint_as_float(v << 16); }
__device__ __forceinline__ float bf_hi(uint32_t v) { return __uint_as_float(v & 0xffff0000u); }
__device__ __forceinline__ uint32_t hmul2(uint32_t a, uint32_t b) { uint32_t r; asm("mul.rn.bf16x2 %0, %1, %2;" : "=r"(r) : "r"(a), "r"(b)); return r; }
__device__ __forceinline__ uint32_t hfma2(uint32_t a, uint32_t b, uint32_t c) { uint32_t r; asm("fma.rn.bf16x2 %0, %1, %2, %3;" : "=r"(r) : "r"(a), "r"(b), "r"(c)); return r; }
__device__ __forceinline__ float rbf(float x) { uint32_t r; asm("cvt.rn.bf16x2.f32 %0, %1, %2;" : "=r"(r) : "f"(x), "f"(0.0f)); return __uint_as_float(r); }
__device__ __forceinline__ void stmatrix4(uint32_t a, uint32_t r0, uint32_t r1, uint32_t r2, uint32_t r3) {
  asm volatile("stmatrix.sync.aligned.m8n8.x4.shared.b16 [%0], {%1,%2,%3,%4};" ::"r"(a), "r"(r0), "r"(r1), "r"(r2), "r"(r3) : "memory");
}
__device__ __forceinline__ void stmatrix2(uint32_t a, uint32_t r0, uint32_t r1) {
  asm volatile("stmatrix.sync.aligned.m8n8.x2.shared.b16 [%0], {%1,%2};" ::"r"(a), "r"(r0), "r"(r1) : "memory");
}
__device__ __forceinline__ uint32_t movm(uint32_t a) { uint32_t r; asm("movmatrix.sync.aligned.m8n8.trans.b16 %0, %1;" : "=r"(r) : "r"(a)); return r; }
template <bool ACC> __device__ __forceinline__ void mma16(float* d, uint32_t a0, uint32_t a1, uint32_t a2, uint32_t a3, uint32_t b0, uint32_t b1) {
  if (ACC) asm("mma.sync.aligned.m16n8k16.row.col.f32.bf16.bf16.f32 {%0,%1,%2,%3}, {%4,%5,%6,%7}, {%8,%9}, {%0,%1,%2,%3};"
               : "+f"(d[0]), "+f"(d[1]), "+f"(d[2]), "+f"(d[3]) : "r"(a0), "r"(a1), "r"(a2), "r"(a3), "r"(b0), "r"(b1));
  else asm("mma.sync.aligned.m16n8k16.row.col.f32.bf16.bf16.f32 {%0,%1,%2,%3}, {%4,%5,%6,%7}, {%8,%9}, {%10,%10,%10,%10};"
           : "=f"(d[0]), "=f"(d[1]), "=f"(d[2]), "=f"(d[3]) : "r"(a0), "r"(a1), "r"(a2), "r"(a3), "r"(b0), "r"(b1), "f"(0.f));
}
__device__ __forceinline__ uint32_t pin(uint32_t v) { uint32_t r; asm volatile("shfl.sync.bfly.b32 %0, %1, 0, 31, 0xffffffff;" : "=r"(r) : "r"(v)); return r; }
template <class T> __device__ __forceinline__ T* pin(T* p) {
  const uint64_t a = reinterpret_cast<uint64_t>(p);
  return reinterpret_cast<T*>((uint64_t)pin((uint32_t)a) | ((uint64_t)pin((uint32_t)(a >> 32)) << 32));
}
__device__ __forceinline__ uint32_t upin(uint32_t v) { return __shfl_sync(0xffffffffu, v, 0); }
template <class T> __device__ __forceinline__ T* upin(T* p) {
  const uint64_t a = reinterpret_cast<uint64_t>(p);
  return reinterpret_cast<T*>((uint64_t)upin((uint32_t)a) | ((uint64_t)upin((uint32_t)(a >> 32)) << 32));
}
__device__ __forceinline__ int lane_id() { int v; asm volatile("mov.u32 %0, %%laneid;" : "=r"(v)); return v; }
__device__ __forceinline__ bool elect() {
  uint32_t p;
  asm volatile("{\n.reg .pred P;\nelect.sync _|P, 0xffffffff;\nselp.u32 %0, 1, 0, P;\n}" : "=r"(p));
  return p;
}
__device__ __forceinline__ uint32_t set_tag(uint32_t w, uint32_t tag) { uint32_t r; asm("lop3.b32 %0, %1, 0xfffffffe, %2, 0xea;" : "=r"(r) : "r"(w), "r"(tag)); return r; }
__device__ __forceinline__ uint32_t bitsel(uint32_t w, uint32_t m, uint32_t o) { uint32_t r; asm("lop3.b32 %0, %1, %2, %3, 0xe2;" : "=r"(r) : "r"(w), "r"(m), "r"(o)); return r; }
__device__ __forceinline__ uint32_t or3(uint32_t a, uint32_t b, uint32_t c) { uint32_t r; asm("lop3.b32 %0, %1, %2, %3, 0xfe;" : "=r"(r) : "r"(a), "r"(b), "r"(c)); return r; }
__device__ __forceinline__ uint32_t diff2(uint32_t a, uint32_t b, uint32_t tag) { uint32_t r; asm("lop3.b32 %0, %1, %2, %3, 0x7e;" : "=r"(r) : "r"(a), "r"(b), "r"(tag)); return r; }
__device__ __forceinline__ float2 cmul(float2 a, float2 b) { return make_float2(a.x * b.x - a.y * b.y, a.x * b.y + a.y * b.x); }

template<int TB> __device__ __forceinline__ void wgmma_ss_160_0(float (&d)[96], uint32_t al, uint32_t ah, uint32_t bl, uint32_t bh) {
  asm volatile("{\n.reg .b64 da, db;\nmov.b64 da, {%80, %81};\nmov.b64 db, {%82, %83};\n"
    "wgmma.mma_async.sync.aligned.m64n160k16.f32.bf16.bf16 {%0,%1,%2,%3,%4,%5,%6,%7,%8,%9,%10,%11,%12,%13,%14,%15,%16,%17,%18,%19,%20,%21,%22,%23,%24,%25,%26,%27,%28,%29,%30,%31,%32,%33,%34,%35,%36,%37,%38,%39,%40,%41,%42,%43,%44,%45,%46,%47,%48,%49,%50,%51,%52,%53,%54,%55,%56,%57,%58,%59,%60,%61,%62,%63,%64,%65,%66,%67,%68,%69,%70,%71,%72,%73,%74,%75,%76,%77,%78,%79}, da, db, 1, 1, 1, 1, %84;\n}\n"
    : "+f"(d[0]),"+f"(d[1]),"+f"(d[2]),"+f"(d[3]),"+f"(d[4]),"+f"(d[5]),"+f"(d[6]),"+f"(d[7]),"+f"(d[8]),"+f"(d[9]),"+f"(d[10]),"+f"(d[11]),"+f"(d[12]),"+f"(d[13]),"+f"(d[14]),"+f"(d[15]),"+f"(d[16]),"+f"(d[17]),"+f"(d[18]),"+f"(d[19]),"+f"(d[20]),"+f"(d[21]),"+f"(d[22]),"+f"(d[23]),"+f"(d[24]),"+f"(d[25]),"+f"(d[26]),"+f"(d[27]),"+f"(d[28]),"+f"(d[29]),"+f"(d[30]),"+f"(d[31]),"+f"(d[32]),"+f"(d[33]),"+f"(d[34]),"+f"(d[35]),"+f"(d[36]),"+f"(d[37]),"+f"(d[38]),"+f"(d[39]),"+f"(d[40]),"+f"(d[41]),"+f"(d[42]),"+f"(d[43]),"+f"(d[44]),"+f"(d[45]),"+f"(d[46]),"+f"(d[47]),"+f"(d[48]),"+f"(d[49]),"+f"(d[50]),"+f"(d[51]),"+f"(d[52]),"+f"(d[53]),"+f"(d[54]),"+f"(d[55]),"+f"(d[56]),"+f"(d[57]),"+f"(d[58]),"+f"(d[59]),"+f"(d[60]),"+f"(d[61]),"+f"(d[62]),"+f"(d[63]),"+f"(d[64]),"+f"(d[65]),"+f"(d[66]),"+f"(d[67]),"+f"(d[68]),"+f"(d[69]),"+f"(d[70]),"+f"(d[71]),"+f"(d[72]),"+f"(d[73]),"+f"(d[74]),"+f"(d[75]),"+f"(d[76]),"+f"(d[77]),"+f"(d[78]),"+f"(d[79])
    : "r"(al), "r"(ah), "r"(bl), "r"(bh), "n"(TB));
}
template<int TB> __device__ __forceinline__ void wgmma_ss_144_0(float (&d)[96], uint32_t al, uint32_t ah, uint32_t bl, uint32_t bh) {
  asm volatile("{\n.reg .b64 da, db;\nmov.b64 da, {%72, %73};\nmov.b64 db, {%74, %75};\n"
    "wgmma.mma_async.sync.aligned.m64n144k16.f32.bf16.bf16 {%0,%1,%2,%3,%4,%5,%6,%7,%8,%9,%10,%11,%12,%13,%14,%15,%16,%17,%18,%19,%20,%21,%22,%23,%24,%25,%26,%27,%28,%29,%30,%31,%32,%33,%34,%35,%36,%37,%38,%39,%40,%41,%42,%43,%44,%45,%46,%47,%48,%49,%50,%51,%52,%53,%54,%55,%56,%57,%58,%59,%60,%61,%62,%63,%64,%65,%66,%67,%68,%69,%70,%71}, da, db, 1, 1, 1, 1, %76;\n}\n"
    : "+f"(d[0]),"+f"(d[1]),"+f"(d[2]),"+f"(d[3]),"+f"(d[4]),"+f"(d[5]),"+f"(d[6]),"+f"(d[7]),"+f"(d[8]),"+f"(d[9]),"+f"(d[10]),"+f"(d[11]),"+f"(d[12]),"+f"(d[13]),"+f"(d[14]),"+f"(d[15]),"+f"(d[16]),"+f"(d[17]),"+f"(d[18]),"+f"(d[19]),"+f"(d[20]),"+f"(d[21]),"+f"(d[22]),"+f"(d[23]),"+f"(d[24]),"+f"(d[25]),"+f"(d[26]),"+f"(d[27]),"+f"(d[28]),"+f"(d[29]),"+f"(d[30]),"+f"(d[31]),"+f"(d[32]),"+f"(d[33]),"+f"(d[34]),"+f"(d[35]),"+f"(d[36]),"+f"(d[37]),"+f"(d[38]),"+f"(d[39]),"+f"(d[40]),"+f"(d[41]),"+f"(d[42]),"+f"(d[43]),"+f"(d[44]),"+f"(d[45]),"+f"(d[46]),"+f"(d[47]),"+f"(d[48]),"+f"(d[49]),"+f"(d[50]),"+f"(d[51]),"+f"(d[52]),"+f"(d[53]),"+f"(d[54]),"+f"(d[55]),"+f"(d[56]),"+f"(d[57]),"+f"(d[58]),"+f"(d[59]),"+f"(d[60]),"+f"(d[61]),"+f"(d[62]),"+f"(d[63]),"+f"(d[64]),"+f"(d[65]),"+f"(d[66]),"+f"(d[67]),"+f"(d[68]),"+f"(d[69]),"+f"(d[70]),"+f"(d[71])
    : "r"(al), "r"(ah), "r"(bl), "r"(bh), "n"(TB));
}
template<int TB> __device__ __forceinline__ void wgmma_ss_96_0(float (&d)[96], uint32_t al, uint32_t ah, uint32_t bl, uint32_t bh) {
  asm volatile("{\n.reg .b64 da, db;\nmov.b64 da, {%48, %49};\nmov.b64 db, {%50, %51};\n"
    "wgmma.mma_async.sync.aligned.m64n96k16.f32.bf16.bf16 {%0,%1,%2,%3,%4,%5,%6,%7,%8,%9,%10,%11,%12,%13,%14,%15,%16,%17,%18,%19,%20,%21,%22,%23,%24,%25,%26,%27,%28,%29,%30,%31,%32,%33,%34,%35,%36,%37,%38,%39,%40,%41,%42,%43,%44,%45,%46,%47}, da, db, 1, 1, 1, 1, %52;\n}\n"
    : "+f"(d[0]),"+f"(d[1]),"+f"(d[2]),"+f"(d[3]),"+f"(d[4]),"+f"(d[5]),"+f"(d[6]),"+f"(d[7]),"+f"(d[8]),"+f"(d[9]),"+f"(d[10]),"+f"(d[11]),"+f"(d[12]),"+f"(d[13]),"+f"(d[14]),"+f"(d[15]),"+f"(d[16]),"+f"(d[17]),"+f"(d[18]),"+f"(d[19]),"+f"(d[20]),"+f"(d[21]),"+f"(d[22]),"+f"(d[23]),"+f"(d[24]),"+f"(d[25]),"+f"(d[26]),"+f"(d[27]),"+f"(d[28]),"+f"(d[29]),"+f"(d[30]),"+f"(d[31]),"+f"(d[32]),"+f"(d[33]),"+f"(d[34]),"+f"(d[35]),"+f"(d[36]),"+f"(d[37]),"+f"(d[38]),"+f"(d[39]),"+f"(d[40]),"+f"(d[41]),"+f"(d[42]),"+f"(d[43]),"+f"(d[44]),"+f"(d[45]),"+f"(d[46]),"+f"(d[47])
    : "r"(al), "r"(ah), "r"(bl), "r"(bh), "n"(TB));
}
template<int TB> __device__ __forceinline__ void wgmma_ss_96_48(float (&d)[96], uint32_t al, uint32_t ah, uint32_t bl, uint32_t bh) {
  asm volatile("{\n.reg .b64 da, db;\nmov.b64 da, {%48, %49};\nmov.b64 db, {%50, %51};\n"
    "wgmma.mma_async.sync.aligned.m64n96k16.f32.bf16.bf16 {%0,%1,%2,%3,%4,%5,%6,%7,%8,%9,%10,%11,%12,%13,%14,%15,%16,%17,%18,%19,%20,%21,%22,%23,%24,%25,%26,%27,%28,%29,%30,%31,%32,%33,%34,%35,%36,%37,%38,%39,%40,%41,%42,%43,%44,%45,%46,%47}, da, db, 1, 1, 1, 1, %52;\n}\n"
    : "+f"(d[48]),"+f"(d[49]),"+f"(d[50]),"+f"(d[51]),"+f"(d[52]),"+f"(d[53]),"+f"(d[54]),"+f"(d[55]),"+f"(d[56]),"+f"(d[57]),"+f"(d[58]),"+f"(d[59]),"+f"(d[60]),"+f"(d[61]),"+f"(d[62]),"+f"(d[63]),"+f"(d[64]),"+f"(d[65]),"+f"(d[66]),"+f"(d[67]),"+f"(d[68]),"+f"(d[69]),"+f"(d[70]),"+f"(d[71]),"+f"(d[72]),"+f"(d[73]),"+f"(d[74]),"+f"(d[75]),"+f"(d[76]),"+f"(d[77]),"+f"(d[78]),"+f"(d[79]),"+f"(d[80]),"+f"(d[81]),"+f"(d[82]),"+f"(d[83]),"+f"(d[84]),"+f"(d[85]),"+f"(d[86]),"+f"(d[87]),"+f"(d[88]),"+f"(d[89]),"+f"(d[90]),"+f"(d[91]),"+f"(d[92]),"+f"(d[93]),"+f"(d[94]),"+f"(d[95])
    : "r"(al), "r"(ah), "r"(bl), "r"(bh), "n"(TB));
}
__device__ __forceinline__ void wgmma_rs_72(float (&d)[36], uint32_t a0, uint32_t a1, uint32_t a2, uint32_t a3, uint32_t bl, uint32_t bh, int sd) {
  asm volatile("{\n.reg .pred p;\n.reg .b64 db;\nsetp.ne.b32 p, %42, 0;\nmov.b64 db, {%40, %41};\n"
    "wgmma.mma_async.sync.aligned.m64n72k16.f32.bf16.bf16 {%0,%1,%2,%3,%4,%5,%6,%7,%8,%9,%10,%11,%12,%13,%14,%15,%16,%17,%18,%19,%20,%21,%22,%23,%24,%25,%26,%27,%28,%29,%30,%31,%32,%33,%34,%35}, {%36,%37,%38,%39}, db, p, 1, 1, 1;\n}\n"
    : "+f"(d[0]),"+f"(d[1]),"+f"(d[2]),"+f"(d[3]),"+f"(d[4]),"+f"(d[5]),"+f"(d[6]),"+f"(d[7]),"+f"(d[8]),"+f"(d[9]),"+f"(d[10]),"+f"(d[11]),"+f"(d[12]),"+f"(d[13]),"+f"(d[14]),"+f"(d[15]),"+f"(d[16]),"+f"(d[17]),"+f"(d[18]),"+f"(d[19]),"+f"(d[20]),"+f"(d[21]),"+f"(d[22]),"+f"(d[23]),"+f"(d[24]),"+f"(d[25]),"+f"(d[26]),"+f"(d[27]),"+f"(d[28]),"+f"(d[29]),"+f"(d[30]),"+f"(d[31]),"+f"(d[32]),"+f"(d[33]),"+f"(d[34]),"+f"(d[35])
    : "r"(a0), "r"(a1), "r"(a2), "r"(a3), "r"(bl), "r"(bh), "r"(sd));
}
__device__ __forceinline__ void wgmma_rs_48(float (&d)[24], uint32_t a0, uint32_t a1, uint32_t a2, uint32_t a3, uint32_t bl, uint32_t bh, int sd) {
  asm volatile("{\n.reg .pred p;\n.reg .b64 db;\nsetp.ne.b32 p, %30, 0;\nmov.b64 db, {%28, %29};\n"
    "wgmma.mma_async.sync.aligned.m64n48k16.f32.bf16.bf16 {%0,%1,%2,%3,%4,%5,%6,%7,%8,%9,%10,%11,%12,%13,%14,%15,%16,%17,%18,%19,%20,%21,%22,%23}, {%24,%25,%26,%27}, db, p, 1, 1, 1;\n}\n"
    : "+f"(d[0]),"+f"(d[1]),"+f"(d[2]),"+f"(d[3]),"+f"(d[4]),"+f"(d[5]),"+f"(d[6]),"+f"(d[7]),"+f"(d[8]),"+f"(d[9]),"+f"(d[10]),"+f"(d[11]),"+f"(d[12]),"+f"(d[13]),"+f"(d[14]),"+f"(d[15]),"+f"(d[16]),"+f"(d[17]),"+f"(d[18]),"+f"(d[19]),"+f"(d[20]),"+f"(d[21]),"+f"(d[22]),"+f"(d[23])
    : "r"(a0), "r"(a1), "r"(a2), "r"(a3), "r"(bl), "r"(bh), "r"(sd));
}
template<int N,int OFF,int TB> __device__ __forceinline__ void wgmma_ss(float (&d)[96], uint32_t al, uint32_t ah, uint32_t bl, uint32_t bh) {
  if constexpr (N==160 && OFF==0) wgmma_ss_160_0<TB>(d, al, ah, bl, bh);
  else if constexpr (N==144 && OFF==0) wgmma_ss_144_0<TB>(d, al, ah, bl, bh);
  else if constexpr (N==96 && OFF==0) wgmma_ss_96_0<TB>(d, al, ah, bl, bh);
  else if constexpr (N==96 && OFF==48) wgmma_ss_96_48<TB>(d, al, ah, bl, bh);
}

__device__ __forceinline__ void dft3(float2& a, float2& b, float2& c) {
  const float s = 0.86602540378443864676f;
  float2 t = make_float2(b.x + c.x, b.y + c.y), d = make_float2(b.x - c.x, b.y - c.y);
  float2 m = make_float2(fmaf(-0.5f, t.x, a.x), fmaf(-0.5f, t.y, a.y));
  a = make_float2(a.x + t.x, a.y + t.y);
  b = make_float2(fmaf(s, d.y, m.x), fmaf(-s, d.x, m.y));
  c = make_float2(fmaf(-s, d.y, m.x), fmaf(s, d.x, m.y));
}
__device__ __forceinline__ void dft9(float2 (&x)[9]) {
  const float2 w1 = make_float2(0.76604444311897803520f, -0.64278760968653932632f);
  const float2 w2 = make_float2(0.17364817766693034885f, -0.98480775301220805937f);
  const float2 w4 = make_float2(-0.93969262078590838405f, -0.34202014332566873304f);
  dft3(x[0], x[3], x[6]); dft3(x[1], x[4], x[7]); dft3(x[2], x[5], x[8]);
  x[4] = cmul(x[4], w1); x[7] = cmul(x[7], w2); x[5] = cmul(x[5], w2); x[8] = cmul(x[8], w4);
  dft3(x[0], x[1], x[2]); dft3(x[3], x[4], x[5]); dft3(x[6], x[7], x[8]);
  float2 t;
  t = x[1]; x[1] = x[3]; x[3] = t;
  t = x[2]; x[2] = x[6]; x[6] = t;
  t = x[5]; x[5] = x[7]; x[7] = t;
}

__device__ __forceinline__ uint32_t* mod_ptr(Scratch* sc, int u, int t128) {
  const int i = t128 & 15;
  return u < 72 ? sc->moda + (t128 >> 4) * (2 * D_) + 16 * u + 2 * (i & 7) + (i >> 3) : sc->mod + 16 * (u - 72) + i;
}
__device__ __forceinline__ void mod_unit(Scratch* sc, int u, int t128, uint32_t sw_, uint32_t bar, int ph, uint32_t rb, uint32_t tag) {
  const int w = t128 >> 5, l = t128 & 31;
  uint32_t b[18];
#pragma unroll
  for (int i = 0; i < 18; i++) b[i] = lds(red + 512 + (72 * w + 4 * i + (l & 3)) * 4);
  const uint32_t sa = pin(sw_ + (144 * w + (l & 7) + 8 * (l >> 4)) * 32 + (((l >> 3) ^ (l >> 2)) & 1) * 16);
  const uint32_t sr = pin(rb + (l >> 2) * 16 + w * 4);
  uint32_t* const dst = pin(mod_ptr(sc, u, t128));
  const int kind = u / 36;
  const float mul = __uint_as_float(pin(__float_as_uint(kind == 0 ? 16.0f : 1.0f))), add = __uint_as_float(pin(__float_as_uint(kind == 1 || kind == 4 ? 1.0f : 0.0f)));
  mbar_wait(bar, ph);
  float d[3][4];
#pragma unroll
  for (int i = 0; i < 9; i++) {
    uint32_t a0, a1, a2, a3;
    asm volatile("ldmatrix.sync.aligned.m8n8.x4.trans.shared.b16 {%0,%1,%2,%3}, [%4];" : "=r"(a0), "=r"(a1), "=r"(a2), "=r"(a3) : "r"(sa + i * 512) : "memory");
    if (i < 3) mma16<false>(d[i], a0, a1, a2, a3, b[2 * i], b[2 * i + 1]);
    else mma16<true>(d[i % 3], a0, a1, a2, a3, b[2 * i], b[2 * i + 1]);
  }
  if ((l & 3) == 0) { sts(sr, __float_as_uint(d[0][0] + d[1][0] + d[2][0])); sts(sr + 128, __float_as_uint(d[0][2] + d[1][2] + d[2][2])); }
  bar_sync(4, 128);
  const uint4 v = lds4(rb + (l & 15) * 16);
  const float m = rbf(fmaf(rbf((__uint_as_float(v.x) + __uint_as_float(v.y)) + (__uint_as_float(v.z) + __uint_as_float(v.w))), mul, add));
  if (u < 72 || t128 < 16) *dst = __float_as_uint(m) | tag;
}

__device__ __forceinline__ float rsq(float x) { float r; asm("rsqrt.approx.ftz.f32 %0, %1;" : "=f"(r) : "f"(x)); return r; }
__device__ __forceinline__ void ln_stats2(const float (&a)[18], const float (&b)[18], float sc, float& oa, float& ra, float& ob, float& rb) {
  float v[4] = {0.f, 0.f, 0.f, 0.f}, w[4] = {0.f, 0.f, 0.f, 0.f};
#pragma unroll
  for (int i = 0; i < 18; i += 2) {
    v[0] += a[i]; v[1] = fmaf(a[i], a[i], v[1]); v[2] += b[i]; v[3] = fmaf(b[i], b[i], v[3]);
    w[0] += a[i + 1]; w[1] = fmaf(a[i + 1], a[i + 1], w[1]); w[2] += b[i + 1]; w[3] = fmaf(b[i + 1], b[i + 1], w[3]);
  }
#pragma unroll
  for (int e = 0; e < 4; e++) v[e] += w[e];
#pragma unroll
  for (int o = 16; o; o >>= 1) {
#pragma unroll
    for (int e = 0; e < 4; e++) v[e] += __shfl_xor_sync(0xffffffffu, v[e], o);
  }
  const float ma = v[0] * (1.0f / D_), mb = v[2] * (1.0f / D_);
  ra = sc * rsq(fmaxf(fmaf(-ma, ma, v[1] * (1.0f / D_)), 0.f) + 1e-5f);
  rb = sc * rsq(fmaxf(fmaf(-mb, mb, v[3] * (1.0f / D_)), 0.f) + 1e-5f);
  oa = -ma * ra; ob = -mb * rb;
}

__device__ __forceinline__ void ln_stats1(const float (&a)[18], float sc, float& oa, float& ra) {
  float v[3] = {a[0], a[1], a[2]}, w[3] = {a[0] * a[0], a[1] * a[1], a[2] * a[2]};
#pragma unroll
  for (int i = 3; i < 18; i++) { v[i % 3] += a[i]; w[i % 3] = fmaf(a[i], a[i], w[i % 3]); }
  float s = v[0] + v[1] + v[2], q = w[0] + w[1] + w[2];
#pragma unroll
  for (int o = 16; o; o >>= 1) { s += __shfl_xor_sync(0xffffffffu, s, o); q += __shfl_xor_sync(0xffffffffu, q, o); }
  const float m = s * (1.0f / D_);
  ra = sc * rsq(fmaxf(fmaf(-m, m, q * (1.0f / D_)), 0.f) + 1e-5f);
  oa = -m * ra;
}

__device__ __forceinline__ float tmat(int c, int q, int j) {
  const int ph = q == 1 ? 1024 * j : (q >> 1) * (c + 128 * j) + 512 * (q & 1);
  return __cosf((float)(((ph + 1024) & 2047) - 1024) * (6.283185307179586f / 2048.0f));
}
__device__ __forceinline__ uint32_t line_off(int k1, int kap, int pi, int f) {
  int kd = 64 * k1 + 9 * kap;
  if (kap == 0 && k1 > 4) kd -= 288;
  if (kd >= D_) kd -= D_;
  return pi * 2400 + ((min(kd, D_ - kd) ^ f) << 3);
}

struct Ring { uint32_t st, ph; };
template <bool G2, class T> __device__ __forceinline__ void ring_next(T& st, T& ph) {
  if (++st == NST) st = 0;
  ph ^= ((G2 ? 0xDu : 0x1u) >> st) & 1;
}
__device__ __forceinline__ void arrive_if(uint32_t a, uint32_t p) {
  asm volatile("{\n.reg .pred p;\nsetp.ne.u32 p, %1, 0;\n@p mbarrier.arrive.shared::cta.b64 _, [%0];\n}" ::"r"(a), "r"(p) : "memory");
}
template <int NA> __device__ __forceinline__ void reg_fence_n(float (&d)[96]) {
#pragma unroll
  for (int i = 0; i < NA; i++) asm volatile("" : "+f"(d[i])::"memory");
}
template <int MODE, class F>
__device__ __forceinline__ void gemm_main(float (&acc)[96], uint32_t da0, uint32_t da1, uint32_t db0, int wg, Ring& rg,
                                          int J, F&& side_work) {
  constexpr int NKB = MODE == 3 ? 36 : 32;
  constexpr uint32_t HA = 0x40000040u, HB = MODE == 3 ? 0xC0000010u : 0x80000020u;
  constexpr uint32_t KA = 2048 >> 4, KB = (MODE == 3 ? 512 : 1024) >> 4;
  constexpr int NA = MODE == 3 ? 72 : MODE == 1 ? 96 : 80;
  const uint32_t t = threadIdx.x & 127;
  const uint32_t eb = full0 + 8 * NST;
  constexpr uint32_t SP = (MODE == 3 ? STAGE2 : STAGE) >> 4;
  uint32_t pb = 0, prel = 0, ok = 0, sn = rg.st * SP;
  int n = MODE != 3 ? X1K + 2 * wg : wg ? NKB - J : NKB, nh = 0, ng = MODE == 3 && !wg;
#pragma unroll 1
  for (int pass = MODE == 3 ? 0 : -1;; pass++) {
#pragma unroll 1
    do {
      mbar_wait(full0 + 8 * rg.st, rg.ph);
#pragma unroll 1
      do {
      const uint32_t so = sn, cb = eb + 8 * rg.st;
      reg_fence_n<NA>(acc);
      if (MODE == 1 && wg) {
        wg_fence();
#pragma unroll
        for (int k = 0; k < 4; k++) wgmma_ss<96, 48, 1>(acc, da1 + so + k * KA, HA, db0 + so + k * KB, HB);
        wg_commit();
      }
      wg_fence();
#pragma unroll
      for (int k = 0; k < 4; k++) {
        if (k == 2) asm volatile("{\n.reg .pred p;\nsetp.eq.s32 p, %0, %1;\n@p bar.arrive 1, 256;\n}" ::"r"(n), "r"(ng) : "memory");
        if (k == 1 && MODE != 1) { wg_commit(); wg_wait<1>(); arrive_if(pb, prel); }
        if (k == 2) { ring_next<MODE == 3>(rg.st, rg.ph); sn = rg.st * SP; ok = mbar_test(full0 + 8 * rg.st, rg.ph); }
        if (MODE == 0) wgmma_ss<160, 0, 1>(acc, da0 + so + k * KA, HA, db0 + so + k * KB, HB);
        else if (MODE == 3) wgmma_ss<144, 0, 1>(acc, da0 + so + k * KA, HA, db0 + so + k * KB, HB);
        else wgmma_ss<96, 0, 1>(acc, da0 + so + k * KA, HA, db0 + so + k * KB, HB);
      }
      wg_commit();
      if (MODE == 1) { wg_wait<1>(); arrive_if(pb, prel); }
      reg_fence_n<NA>(acc);
      pb = cb; prel = t == 0 && (MODE != 0 || n != nh);
      } while (--n && ok);
    } while (n);
    if (pass == wg) break;
    if (MODE != 3 && pass < 0) {
      side_work();
      n = NKB - X1K - (J + 2) * wg;
      if (!wg) { ng = 1; if (J < NST) nh = NST; }
      continue;
    }
    wg_wait<0>();
    arrive_if(pb, prel);
    prel = 0;
    n = J;
    if (MODE == 0 && J < NST) bar_arrive(11, 256);
    bar_sync(1, 256);
  }
  if (MODE == 0 && J < NST && !wg) bar_sync(11, 256);
  wg_wait<0>();
  reg_fence_n<NA>(acc);
  if (MODE != 3) arrive_if(pb, prel);
}

constexpr float GK1 = 2.0f * 0.7978845608028654f, GK3 = 8.0f * 0.044715f * 0.7978845608028654f;

__device__ __forceinline__ int kb2_order(int i) { const int wv = i / 6; return 6 * (i - 6 * wv) + ((0x431250 >> (4 * wv)) & 7); }

__device__ __forceinline__ int kb2_pos(int kb) { const int hf = kb >= 36, k = kb - 36 * hf, gr = k / 6; return 64 * hf + gr + 6 * ((0x154230 >> (4 * (k - 6 * gr))) & 7); }

__device__ __forceinline__ void wait_flags(const unsigned* p, int idx, unsigned target, uint32_t& ready) {
  int it = 0;
  while (!((ready >> idx) & 1) && it++ < SPIN_MAX) ready = __ballot_sync(0xffffffffu, (int)(ld_rlx(p) - target) >= 0);
}

enum { B_FULL = 0, B_EMPTY = 6, B_S4 = 12, B_S5, B_LAND, B_FLT = B_LAND + 6, B_Z1, B_Z2, B_GO, B_X, B_WM, B_NUM, B_W0 = B_NUM };

__global__ void __launch_bounds__(NTHR, 1)
fused_kernel(const Params p, const __grid_constant__ Maps maps) {
  extern __shared__ __align__(1024) uint8_t smem_raw[];
  const int bx = blockIdx.x, cta = bx < 112 || bx >= 130 ? bx : bx < 114 ? bx + 16 : bx - 2;
  const int tid = threadIdx.x, t128 = tid & 127;
  const int wp = __shfl_sync(0xffffffffu, tid >> 5, 0), wg = wp >> 2;
  const int l = tid & 31, g = l >> 2, t = l & 3;
  Scratch* const sc = p.s;
  const bool rows = cta < 128;
  const int mu = rows ? cta + 4 : cta - 128;
  const int R = mu - 12;

  uint32_t xr[18];
  uint32_t cv[3];
  const unsigned ep0 = ld_rlx(&sc->cnt[C_EP + l]);
  if (wg == 2) {
#pragma unroll
    for (int i = 0; i < 3; i++) cv[i] = ld_nc(reinterpret_cast<const uint32_t*>(p.c) + min(t128 + 128 * i, 287));
    if (wp == 9 && l < 9 && rows) {
      const int h = 9 * cta + l;
      prefetch_l2(reinterpret_cast<const uint8_t*>(p.wmod) + (size_t)(h >> 1) * (12 * D_) + (h & 1) * (2 * D_), 2 * D_);
    }
    if (tid == 256 && mu < 72) {
      mbar_init(full0 + 8 * B_W0, 1);
      fence_async_smem();
      mbar_expect(full0 + 8 * B_W0, 18432);
#pragma unroll 1
      for (int i = 0; i < 3; i++) tma2d(sbase + O_P2 + i * 6144, &maps.wm, 16 * mu, 192 * i, full0 + 8 * B_W0);
    }
    __syncwarp();
#pragma unroll 1
    for (int u = mu < 72 ? mu : 72 + mu; u < 216; u += u < 72 ? 72 : NCTA) if (u < 72 || t128 < 16) *mod_ptr(sc, u, t128) = 0;
    if (wp == 11 && smem_u32(smem_raw) != sbase) __trap();
    if (wp >= 10 && elect()) {
#pragma unroll 1
      for (int i = wp - 10; i < B_NUM; i += 2) mbar_init(full0 + 8 * i, i == B_FLT ? 4 : i == B_WM ? 3 : i < B_S4 ? 2 : 1);
      fence_async_smem();
    }
    __syncwarp();
  } else if (rows) {
    const uint32_t* xs = reinterpret_cast<const uint32_t*>(p.x) + (size_t)(cta + 128 * ((wp & 3) + 8 * wg)) * 288 + l;
#pragma unroll
    for (int i = 0; i < 9; i++) { xr[i] = ld_nc(xs + 32 * i); xr[9 + i] = ld_nc(xs + 512 * 288 + 32 * i); }
  }
  if (tid == 64 && cta == NCTA - 1) prefetch_l2(p.tab, sizeof(T_TAB));
  __syncwarp();
  auto tag_of = [](unsigned e) { return (e & 0x7fffu) | 0x8000u; };
  const int kap = 8 * ((wp & 3) ^ (wg & 1)) + g;
  uint32_t tb[4], sb1[3], lo[9];
#pragma unroll
  for (int i = 0; i < 4; i++) tb[i] = pin(pack_bf16(tmat(cta, 8 * (i >> 1) + g, t + 8 * (i & 1)), tmat(cta, 8 * (i >> 1) + g, t + 8 * (i & 1) + 4)));
#pragma unroll
  for (int i = 0; i < 3; i++) {
    const int d = 48 * wp + 16 * i + (l & 15);
    sb1[i] = pin(sbase + O_B1 + (l >> 4) * 9216 + (d % 9) * 1024 + (d & 63) * 16);
  }
#pragma unroll
  for (int k1 = 0; k1 < 9; k1++) lo[k1] = pin(sbase + O_Z1 + line_off(k1, kap, 4 * wg + t, cta & 3));
  const uint32_t snt = pin(sbase + O_NRM + ((l & 7) + 8 * (l >> 4)) * 1168 + (48 * wp + (l & 8)) * 2), sn = pin(sbase + O_NRM + wp * 2336 + l * 4);
  const uint32_t smask = pin(t ? 0u : 0xffff0000u);
  const uint32_t* const mp = pin(sc->moda + (cta >> 4) * (2 * D_) + 48 * wp + 2 * g);
  const uint4* const ftab = pin(p.tab + TB_F + (t128 ^ (wg << 5)));

  if (wg == 2) {
#pragma unroll
    for (int i = 0; i < 3; i++) {
      const float c0 = bf_lo(cv[i]), c1 = bf_hi(cv[i]);
      sts(red + 512 + min(t128 + 128 * i, 287) * 4, pack_bf16(__fdividef(c0, 1.0f + __expf(-c0)), __fdividef(c1, 1.0f + __expf(-c1))));
    }
    if (t128 == 0) sts(full0 + 248, ep0 + 1);
    if (wp == 9 && l < 11) asm volatile("prefetch.tensormap [%0];" ::"l"(&maps.z1 + l) : "memory");
    bar_sync(4, 128);
    if (mu < 72) {
      mod_unit(sc, mu, t128, sbase + O_P2, full0 + 8 * B_W0, 0, red, tag_of(upin(ep0) + 1));
    }
  }
  const int pi = R / 15, col0 = 20 * (R - 15 * pi);
  const int xu = DF_ * pi + col0, xv = DF_ * (pi ? 16 - pi : 8) + col0;
  auto load_filter = [&](int a) {
    const int x = (a & 1) ? xv : xu;
    const bool wide = (x & 15) > 12;
    mbar_expect(full0 + 8 * B_FLT, wide ? 12288 : 8192);
    tma2d(sbase + O_RAW + a * 12288, &maps.wf[a & 2], x & ~15, 0, full0 + 8 * B_FLT);
    if (wide) tma2d(sbase + O_RAW + a * 12288 + 8192, &maps.wf[(a & 2) + 1], (x & ~15) + 32, 0, full0 + 8 * B_FLT);
  };
  uint4 af[4];
  if (rows) {
    uint2 ms[3], mc[3];
    auto load_mod = [&](uint32_t o = 0) {
#pragma unroll
      for (int i = 0; i < 3; i++) { ms[i] = ld_rlx2(mp + 2 * o + 16 * i); mc[i] = ld_rlx2(mp + 2 * o + D_ + 16 * i); }
    };
    if (wg < 2) {
      float a[18], b[18];
#pragma unroll
      for (int i = 0; i < 9; i++) { a[2 * i] = bf_lo(xr[i]); a[2 * i + 1] = bf_hi(xr[i]); b[2 * i] = bf_lo(xr[9 + i]); b[2 * i + 1] = bf_hi(xr[9 + i]); }
      float oa, ra, ob, rb;
      ln_stats2(a, b, 1.0f, oa, ra, ob, rb);
      load_mod((__float_as_uint(ra) | __float_as_uint(rb)) >> 31);
#pragma unroll
      for (int i = 0; i < 9; i++) {
        sts(sn + i * 128, pack_bf16(fmaf(a[2 * i], ra, oa), fmaf(a[2 * i + 1], ra, oa)));
        sts(sn + 1168 + i * 128, pack_bf16(fmaf(b[2 * i], rb, ob), fmaf(b[2 * i + 1], rb, ob)));
      }
      bar_arrive(10, NTHR);
#pragma unroll
      for (int kk = 0; kk < 4; kk++) af[kk] = ld_nc4(ftab + kk * 128);
      bar_sync(1, 256);
    } else {
      bar_sync(10, NTHR);
      load_mod();
      if (wp >= 10 && elect()) prefetch_l2(reinterpret_cast<const uint8_t*>(wp == 10 ? p.wr : p.wi) + cta * 9248, 9248);
      __syncwarp();
    }
    float rs[3][8];
#pragma unroll
    for (int i = 0; i < 3; i++) {
      uint32_t a0, a1, a2, a3;
      asm volatile("ldmatrix.sync.aligned.m8n8.x4.trans.shared.b16 {%0,%1,%2,%3}, [%4];" : "=r"(a0), "=r"(a1), "=r"(a2), "=r"(a3)
                   : "r"(snt + 32 * i) : "memory");
      mma16<false>(&rs[i][0], a0, a1, a2, a3, tb[0], tb[1]);
      mma16<false>(&rs[i][4], a0, a1, a2, a3, tb[2], tb[3]);
    }
    const uint32_t tag16 = tag_of(upin(ep0) + 1), tag1 = tag16 & 1;
    {
      int it = 0;
#pragma unroll 1
      while (true) {
        uint32_t bad = 0;
#pragma unroll
        for (int i = 0; i < 3; i++) bad |= diff2(ms[i].x, ms[i].y, tag16) | diff2(mc[i].x, mc[i].y, tag16);
        if (!any(bad & 0xffffu) || ++it > SPIN_MAX) break;
        load_mod();
      }
#pragma unroll
      for (int i = 0; i < 3; i++) {
        const float c0 = bf_hi(mc[i].x), c1 = bf_hi(mc[i].y);
        const float s0 = __uint_as_float(ms[i].x & smask), s1 = __uint_as_float(ms[i].y & smask);
        stmatrix4(sb1[i], pack_bf16(fmaf(rs[i][0], c0, s0), rs[i][1] * c0), pack_bf16(fmaf(rs[i][2], c1, s1), rs[i][3] * c1),
                  pack_bf16(rs[i][4] * c0, rs[i][5] * c0), pack_bf16(rs[i][6] * c1, rs[i][7] * c1));
      }
    }
    fence_async_smem();
    if (wg == 2) {
      bar_arrive(5, NTHR);
      if (R >= 0 && elect()) load_filter(wp - 8);
      __syncwarp();
      const int slot = 4 * (cta & 7) + ((cta >> 4) & 3) + 32 * (2 * (cta >> 6) + ((cta >> 3) & 1));
      const uint32_t c0 = upin(40 * slot), c1 = upin(60 * (wp & 1)), src = upin(sbase + O_Z1 + (wp & 1) * 9600);
      const CUtensorMap* mz = upin(&maps.z1);
      unsigned* hint = pin(sc->cnt + C_Z1 + 32 * (wp & 1));
      if (wp < 10) {
        bar_sync(2 + (wp & 1), 160);
        if (elect()) tma_st2d(mz, src, c0, c1);
        pause(HD1);
        if (elect()) red_add(hint, 1);
        bulk_commit_wait();
        __syncwarp();
      }
    } else {
      bar_sync(5, NTHR);
      float acc[36];
      const uint32_t db = (((sbase + O_B1 + wg * 9216) & 0x3FFFF) >> 4) | ((128 >> 4) << 16);
      wg_fence();
#pragma unroll
      for (int kk = 0; kk < 4; kk++) wgmma_rs_72(acc, af[kk].x, af[kk].y, af[kk].z, af[kk].w, db + kk * 16, 1024 >> 4, kk);
      wg_commit();
      wg_wait<0>();
      reg_fence(acc);
      float2 za[9], zb[9];
#pragma unroll
      for (int i = 0; i < 9; i++) { za[i] = make_float2(acc[4 * i], acc[4 * i + 2]); zb[i] = make_float2(acc[4 * i + 1], acc[4 * i + 3]); }
      dft9(za); dft9(zb);
      if ((wp & 3) == wg) {
        const float sp = g ? 0.f : 1.f;
#pragma unroll
        for (int k = 1; k < 5; k++) {
          float2 a = za[k], b = za[9 - k];
          za[k] = make_float2(fmaf(sp, b.x, a.x), fmaf(-sp, b.y, a.y)); za[9 - k] = make_float2(fmaf(-sp, a.x, b.x), fmaf(sp, a.y, b.y));
          a = zb[k]; b = zb[9 - k];
          zb[k] = make_float2(fmaf(sp, b.x, a.x), fmaf(-sp, b.y, a.y)); zb[9 - k] = make_float2(fmaf(-sp, a.x, b.x), fmaf(sp, a.y, b.y));
        }
        const uint32_t w0 = set_tag(pack_bf16(za[0].y, 0.f), tag1), w1 = pack_bf16(zb[0].y, 0.f);
        asm volatile("{\n.reg .pred p;\nsetp.eq.u32 p, %3, 0;\n@p st.shared.v2.b32 [%0], {%1,%2};\n}" ::"r"(lo[0] + 288 * 8), "r"(w0), "r"(w1), "r"(g) : "memory");
        za[0].y = g ? za[0].y : 0.f; zb[0].y = g ? zb[0].y : 0.f;
      }
#pragma unroll
      for (int k1 = 0; k1 < 9; k1++) sts2(lo[k1], set_tag(pack_bf16(za[k1].x, za[k1].y), tag1), pack_bf16(zb[k1].x, zb[k1].y));
      fence_async_smem();
      bar_arrive(2 + wg, 160);
      {
        const uint32_t fx = (((cta >> 4) ^ cta) & 3) << 3, dl = O_IN - O_Z1, st = sbase + O_ST + 15360 + tid * 16;
        sts4(st, (lo[0] ^ fx) + dl, (lo[1] ^ fx) + dl, (lo[2] ^ fx) + dl, (lo[3] ^ fx) + dl);
        sts4(st + 4096, (lo[4] ^ fx) + dl, (lo[5] ^ fx) + dl, (lo[6] ^ fx) + dl, (lo[7] ^ fx) + dl);
        sts4(st + 8192, (lo[8] ^ fx) + dl, (lo[0] ^ fx) + dl + (kap ? 0 : 288 * 8),
             sbase + O_B3 + wg * 1024 + (l >> 4) * 2048 + (2 * (kap & 24) + (l & 15)) * 16, 0);
      }
    }
    {
      uint32_t sy[6];
#pragma unroll
      for (int i = 0; i < 6; i++) {
        const int rr = 16 * (wp & 3) + g + 8 * (i & 1);
        sy[i] = sbase + O_Y + (t * 584 + 64 * ((3 * wg + (i >> 1) + 63 - rr) % 9) + rr) * 4;
      }
      sts4(sbase + O_ST + tid * 16, movm(tb[0]), movm(tb[2]), movm(tb[1]), movm(tb[3]));
      sts4(sbase + O_ST + 6144 + tid * 16, sy[0], sy[1], sy[2], sy[3]);
      sts2(sbase + O_ST + 12288 + tid * 8, sy[4], sy[5]);
    }
  } else {
    __syncthreads();
  }

  const unsigned ep = upin(lds(full0 + 248));
  const uint32_t tag16 = tag_of(ep), tag1 = ep & 1;
  auto load_wm = [&](int u) {
    if (wp > 8 && elect()) {
      mbar_expect(full0 + 8 * B_WM, 6144);
      tma2d(sbase + O_NRM + (wp - 9) * 6144, &maps.wm, 16 * u, 192 * (wp - 9), full0 + 8 * B_WM);
    }
    __syncwarp();
  };
  if (R >= 0) {
    const int nl = (col0 + wp < DF_) + (wg < 2 && col0 + wp + 12 < DF_);
    uint4 cf[2][4], G[4];
#pragma unroll
    for (int i = 0; i < 4; i++) {
      cf[0][i] = __ldg(p.tab + TB_P2 + i * 32 + l);
      cf[1][i] = __ldg(p.tab + TB_P2 + (pi ? i : 4 + i) * 32 + l);
      G[i] = __ldg(p.tab + TB_P2 + (8 + i) * 32 + l);
    }
    const uint32_t* zin = sc->z1 + (size_t)R * 5120;
    if (wp == 10) {
      const uint32_t* zu = upin(zin);
      if (elect()) mbar_expect(full0 + 8 * B_Z1, 20480);
      wait_cnt(sc->cnt + C_Z1 + 32 * (pi >> 2), 128 * ep);
      if (elect()) {
        bulk_ld(sbase + O_P2, zu, 20480, full0 + 8 * B_Z1);
      }
      __syncwarp();
    }
    mbar_wait(full0 + 8 * B_FLT, 0);
    float wn[16], wc[16];
#pragma unroll 1
    for (int ln = nl - 1; ln >= 0; ln--) {
      const int col = col0 + wp + 12 * ln, k2 = (57 * col) & 63;
      const bool cj = k2 > 32;
      const float nr = ((col & 31) == 0 && col != 0 && col != 288 ? 0.5f : 1.0f) / ((float)S_ * D_), ni = cj ? -nr : nr;
#pragma unroll
      for (int i = 0; i < 16; i++) wn[i] = wc[i];
#pragma unroll
      for (int cl = 0; cl < 2; cl++) {
        const int v = cl ^ (cj && pi), e = ((v ? xv : xu) & 15) + wp + 12 * ln, sh = e < 32 ? 6 : 5;
        const uint32_t base = sbase + O_RAW + v * 12288 + (e < 32 ? 2 * e : 8192 - 64 + 2 * e), msk = e < 32 ? 0x30 : 0x10;
        const int dm = v ? (cj || pi ? -1 : 0) : 0;
#pragma unroll
        for (int tt = 0; tt < 4; tt++) {
          const int kc = g + 64 * (tt >> 1) + 16 * t + 8 * (tt & 1);
          uint32_t a = base + ((((cj ? -kc : kc) + dm) & 127) << sh);
          a ^= (a >> 3) & msk;
          wc[4 * tt + 2 * cl] = lds_bf(a) * nr; wc[4 * tt + 2 * cl + 1] = lds_bf(a + 24576) * ni;
        }
      }
    }
    const float al = __uint_as_float(pin((pi ? 0x3f800000u : 0u) + (l >> 5)));
    const uint32_t tagv = pin(tag1 + (l >> 5));
    uint32_t off = pin(l * 160 + ((wp ^ (g & 3)) << 3));
    uint32_t offo = pin(sbase + O_P2 + 20480 + off - 64 * l), po = 3072;
    unsigned* hz2 = pin(sc->cnt + C_Z2);
    const uint32_t do2 = pin(12288 - 32 * l);
    const CUtensorMap* mz2 = upin(&maps.z2[wp == 0]);
    const uint32_t sz2 = upin(sbase + O_P2 + 20480 + (wp ? 0 : 12288)), cz2 = upin(40 * R + (wp ? 0 : 24));
    mbar_wait(full0 + 8 * B_Z1, 0);
    if (wg == 2) load_wm(72 + mu);
    uint2 v[4], v2[4];
    const uint32_t o2 = nl > 1 ? 96 : 0;
#pragma unroll
    for (int i = 0; i < 4; i++) { v[i] = lds2(sbase + O_P2 + off + i * 5120); v2[i] = lds2(sbase + O_P2 + off + o2 + i * 5120); }
    auto bad2 = [&]() {
      return any(or3(or3(diff2(v[0].x, v[1].x, tagv), diff2(v[2].x, v[3].x, tagv), diff2(v2[0].x, v2[1].x, tagv)), diff2(v2[2].x, v2[3].x, tagv), 0) & 1);
    };
    if (__builtin_expect(bad2() && nl, 0)) {
      int it = 0;
      do {
#pragma unroll
        for (int i = 0; i < 4; i++) {
          v[i] = ld_rlx2(reinterpret_cast<const uint8_t*>(zin) + off + i * 5120);
          v2[i] = ld_rlx2(reinterpret_cast<const uint8_t*>(zin) + off + o2 + i * 5120);
        }
      } while (bad2() && ++it < SPIN_MAX);
    }
#pragma unroll 1
    for (int ln = 0; ln < nl; ln++, offo += do2, po = 2048) {
      float d[4][4];
      uint32_t A[8];
#pragma unroll
      for (int h = 0; h < 2; h++) {
        mma16<false>(d[2 * h], cf[0][0].x, cf[0][0].y, cf[0][0].z, cf[0][0].w, v[h].x, v[2 + h].x);
        mma16<false>(d[2 * h + 1], cf[1][0].x, cf[1][0].y, cf[1][0].z, cf[1][0].w, v[h].y, v[2 + h].y);
      }
      if (ln) { fence_async_smem(); bar_arrive(15, NTHR); }
#pragma unroll
      for (int h = 0; h < 2; h++)
#pragma unroll
        for (int L = 0; L < 2; L++) {
          const uint4 tw = cf[L][2 + h];
          const float* z = d[2 * h + L];
          const float2 z0 = cmul(make_float2(z[0], z[2]), make_float2(__uint_as_float(tw.x), __uint_as_float(tw.y)));
          const float2 z1 = cmul(make_float2(z[1], z[3]), make_float2(__uint_as_float(tw.z), __uint_as_float(tw.w)));
          A[4 * h + L] = pack_bf16(z0.x, z0.y); A[4 * h + 2 + L] = pack_bf16(z1.x, z1.y);
        }
#pragma unroll
      for (int tt = 0; tt < 4; tt++) {
        mma16<false>(d[tt], A[0], A[1], A[2], A[3], G[tt].x, G[tt].y);
        mma16<true>(d[tt], A[4], A[5], A[6], A[7], G[tt].z, G[tt].w);
      }
#pragma unroll
      for (int tt = 0; tt < 4; tt++) {
        const float ar = d[tt][0], aj = d[tt][1], br = d[tt][2], bj = d[tt][3];
        const float2 y1 = cmul(make_float2(fmaf(-al, bj, ar), fmaf(al, br, aj)), make_float2(wc[4 * tt], wc[4 * tt + 1]));
        const float2 y2 = cmul(make_float2(fmaf(al, ar, bj), fmaf(al, aj, -br)), make_float2(wc[4 * tt + 2], wc[4 * tt + 3]));
        A[2 * tt] = pack_bf16(fmaf(al, y2.x, y1.x), fmaf(-al, y2.y, -y1.y));
        A[2 * tt + 1] = pack_bf16(fmaf(al, y1.y, -y2.y), fmaf(al, y1.x, -y2.x));
      }
#pragma unroll
      for (int i = 0; i < 16; i++) wc[i] = wn[i];
#pragma unroll
      for (int i = 0; i < 4; i++) v[i] = v2[i];
#pragma unroll
      for (int tt = 0; tt < 4; tt++) {
        mma16<false>(d[tt], A[0], A[1], A[2], A[3], G[tt].x, G[tt].y);
        mma16<true>(d[tt], A[4], A[5], A[6], A[7], G[tt].z, G[tt].w);
      }
#pragma unroll
      for (int h = 0; h < 2; h++)
#pragma unroll
        for (int L = 0; L < 2; L++) {
          const uint4 tw = cf[L][2 + h];
          const float2 z0 = cmul(make_float2(d[2 * h][2 * L], d[2 * h][2 * L + 1]), make_float2(__uint_as_float(tw.x), __uint_as_float(tw.y)));
          const float2 z1 = cmul(make_float2(d[2 * h + 1][2 * L], d[2 * h + 1][2 * L + 1]), make_float2(__uint_as_float(tw.z), __uint_as_float(tw.w)));
          A[4 * h + 2 * L] = movm(pack_bf16(z0.x, z1.x)); A[4 * h + 2 * L + 1] = movm(pack_bf16(z0.y, z1.y));
        }
#pragma unroll
      for (int h = 0; h < 2; h++) {
        mma16<false>(d[0], cf[0][1].x, cf[0][1].y, cf[0][1].z, cf[0][1].w, A[4 * h], A[4 * h + 1]);
        mma16<false>(d[1], cf[1][1].x, cf[1][1].y, cf[1][1].z, cf[1][1].w, A[4 * h + 2], A[4 * h + 3]);
#pragma unroll
        for (int e = 0; e < 2; e++)
          sts2(offo + (2 * h + e) * po, set_tag(pack_bf16(d[0][e], d[0][2 + e]), tagv), pack_bf16(d[1][e], d[1][2 + e]));
      }
    }
    fence_async_smem();
    if (nl < 2 && wp != 8) bar_arrive(15, NTHR);
    if (wp) bar_arrive(6, NTHR);
    if (!(wp & 7)) {
      bar_sync(wp ? 15 : 6, NTHR);
      if (elect()) tma_st2d(mz2, sz2, cz2, 0);
      if (wp == 0 && elect()) red_add(hz2, 1);
      if (wp == 0) bulk_commit_wait();
      __syncwarp();
    }
  }
  if (wg == 2) {
#pragma unroll 1
    for (int u = 72 + mu, k = 0; u < 216; u += NCTA, k ^= 1) {
      if (R < 0) { fence_async_smem(); bar_sync(4, 128); load_wm(u); }
      mod_unit(sc, u, t128, sbase + O_NRM, full0 + 8 * B_WM, k, red + 256 - 256 * k, tag16);
    }
    fence_async_smem();
  }

  const int grp = bx / 11, m1 = bx - 11 * grp;
  const bool helper = (m1 & 3) == 3;
  const int f1 = 384 * grp + (helper ? 192 : 128) * (m1 >> 2);
  const int d1 = 160 * (m1 & 3), flip = m1 >= 7;
  const int a1bytes = helper ? 24576 : 16384;
  auto load_a1 = [&](int st, int kb) {
    mbar_expect(full0 + 8 * st, a1bytes);
    tma4d_ef(sbase + st * STAGE, helper ? &maps.w1b : &maps.w1a, 4 * (kb >> 3), 16 * (kb & 7), f1 >> 6, full0 + 8 * st);
  };

  uint32_t bia[4];
  if (wg < 2) {
    const int fa = f1 + (helper ? 128 : 64) * (wg ^ flip) + 16 * (wp & 3) + g, fb = helper ? f1 + 64 + 16 * (wp & 3) + g : fa;
#pragma unroll
    for (int i = 0; i < 4; i++) asm volatile("ld.global.nc.u16 %0, [%1];" : "=r"(bia[i]) : "l"(p.b1 + (i < 2 ? fa : fb) + 8 * (i & 1)) : "memory");
  }
  if (rows) {
#pragma unroll
    for (int kk = 0; kk < 4; kk++) af[kk] = __ldg(p.tab + TB_E + kk * 128 + t128);
    const uint4 c0 = lds4(sbase + O_ST + tid * 16), c1 = lds4(sbase + O_ST + 6144 + tid * 16);
    const uint2 c2 = lds2(sbase + O_ST + 12288 + tid * 8);
    const uint32_t tc[4] = {c0.x, c0.y, c0.z, c0.w}, sy[6] = {c1.x, c1.y, c1.z, c1.w, c2.x, c2.y};
    const uint32_t l8 = pin(8 * l), syl = pin(sbase + O_Y + wp * 2336 + 8 * l);
    uint32_t sh3[3], ham[3];
#pragma unroll
    for (int k = 0; k < 3; k++) {
      const int pos = k && (l >> 4) == k - 1 ? 2 * (l & 6) + ((l >> 2) & 2) + (l & 1) : l & 15;
      const int sw = 2 * cta + ((wp >> 1) & 1), ph = pos ^ ((sw & 3) << 2);
      sh3[k] = pin((l >> 4) * 256 + (wp & 3) * 64 + ph * 4);
      ham[k] = pin(((ph ^ sw) & 7) == 0 ? ~1u : ~0u);
    }
    unsigned* const hh3 = upin(sc->cnt + C_H3 + (cta >> 4));
    uint8_t* const h3g = pin(sc->h3 + (cta >> 4) * (18 * 4096) + (cta & 15) * 256 + (l >> 4) * 3840);
    const int slot = 4 * (cta >> 4) + ((cta >> 1) & 3) + 32 * (2 * ((cta >> 3) & 1) + (cta & 1));
    const uint32_t* zin = sc->z2 + (size_t)slot * 4800;
    if (wg == 2) {
      {
        uint4 v[4];
        const int i3 = min(t128 + 384, 431);
        int it = 0;
        while (true) {
          uint32_t bad = 0;
#pragma unroll
          for (int k = 0; k < 4; k++) v[k] = ld_rlx4(sc->mod + 4 * (k < 3 ? t128 + 128 * k : i3));
#pragma unroll
          for (int k = 0; k < 4; k++) {
            v[k].x ^= tag16; v[k].y ^= tag16; v[k].z ^= tag16; v[k].w ^= tag16;
            bad |= v[k].x | v[k].y | v[k].z | v[k].w;
          }
          if (!any(bad & 0xffffu) || ++it > SPIN_MAX) break;
        }
#pragma unroll
        for (int k = 0; k < 4; k++) sts4(sbase + O_MOD + 16 * (k < 3 ? t128 + 128 * k : i3), v[k].x, v[k].y, v[k].z, v[k].w);
      }
      bulk_commit_wait();
      bar_sync(10, NTHR);
      mbar_wait(full0 + 8 * B_Z2, 0);
      if (elect()) {
        load_a1(wp - 8, wp - 8);
      }
      __syncwarp();
    } else {
      const uint4 e0 = lds4(sbase + O_ST + 15360 + tid * 16), e1 = lds4(sbase + O_ST + 19456 + tid * 16), e2 = lds4(sbase + O_ST + 23552 + tid * 16);
      const uint32_t li[9] = {e0.x, e0.y, e0.z, e0.w, e1.x, e1.y, e1.z, e1.w, e2.x}, lx = e2.y, sb3 = e2.z;
      bar_arrive(10, NTHR);
      if (wp == 1) {
        const uint32_t* zu = upin(zin);
        if (elect()) mbar_expect(full0 + 8 * B_Z2, 19200);
        wait_cnt(sc->cnt + C_Z2, 120 * ep);
        if (elect()) {
          bulk_ld(sbase + O_IN, zu, 19200, full0 + 8 * B_Z2);
        }
        __syncwarp();
      }
      mbar_wait(full0 + 8 * B_Z2, 0);
      uint2 v[10];
#pragma unroll
      for (int k1 = 0; k1 < 10; k1++) v[k1] = lds2(k1 < 9 ? li[k1] : lx);
      float2 za[9], zb[9];
      int it = 0;
#pragma unroll 1
      while (true) {
      const uint32_t bad = or3(or3(diff2(v[0].x, v[1].x, tag1), diff2(v[2].x, v[3].x, tag1), diff2(v[4].x, v[5].x, tag1)), diff2(v[6].x, v[7].x, tag1), diff2(v[8].x, v[9].x, tag1));
#pragma unroll
      for (int i = 0; i < 9; i++) { za[i] = make_float2(bf_lo(v[i].x), bf_hi(v[i].x)); zb[i] = make_float2(bf_lo(v[i].y), bf_hi(v[i].y)); }
      if ((wp & 3) == wg) {
        const float sp = g ? 0.f : 1.f;
#pragma unroll
        for (int k = 1; k < 5; k++) {
          float2 a = za[k], b = za[9 - k];
          za[k] = make_float2(fmaf(-sp, b.x, a.x), fmaf(sp, b.y, a.y)); za[9 - k] = make_float2(fmaf(sp, a.x, b.x), fmaf(-sp, a.y, b.y));
          a = zb[k]; b = zb[9 - k];
          zb[k] = make_float2(fmaf(-sp, b.x, a.x), fmaf(sp, b.y, a.y)); zb[9 - k] = make_float2(fmaf(sp, a.x, b.x), fmaf(-sp, a.y, b.y));
        }
        za[0].y = g ? za[0].y : bf_lo(v[9].x); zb[0].y = g ? zb[0].y : bf_lo(v[9].y);
      }
      dft9(za); dft9(zb);
#pragma unroll
      for (int n = 0; n < 8; n += 2) {
        const int i0 = (9 - n) % 9, i1 = 8 - n;
        stmatrix4(sb3 + n * 2048, pack_bf16(za[i0].x, zb[i0].x), pack_bf16(za[i0].y, zb[i0].y), pack_bf16(za[i1].x, zb[i1].x), pack_bf16(za[i1].y, zb[i1].y));
      }
      stmatrix2(sb3 + 8 * 2048, pack_bf16(za[1].x, zb[1].x), pack_bf16(za[1].y, zb[1].y));
      if (__builtin_expect(!any(bad & 1) || ++it > SPIN_MAX, 1)) break;
#pragma unroll
      for (int k1 = 0; k1 < 10; k1++) v[k1] = ld_rlx2(reinterpret_cast<const uint8_t*>(zin) + (pin(k1 < 9 ? li[k1] : lx) - (sbase + O_IN)));
      }
      fence_async_smem();
    }
    __syncthreads();
    float acc[24];
    const uint32_t db = (((sbase + O_B3 + wg * 6144) & 0x3FFFF) >> 4) | ((128 >> 4) << 16);
    wg_fence();
#pragma unroll
    for (int kk = 0; kk < 4; kk++) wgmma_rs_48(acc, af[kk].x, af[kk].y, af[kk].z, af[kk].w, db + kk * 16, 1024 >> 4, kk);
    wg_commit();
    uint32_t ga[9];
    if (wg < 2) {
#pragma unroll
      for (int i = 0; i < 9; i++) { const uint2 v = lds2(l8 + sbase + O_MOD + 256 * i); ga[i] = __byte_perm(v.x, v.y, 0x7632); }
    }
    wg_wait<0>();
    reg_fence(acc);
#pragma unroll
    for (int i = 0; i < 3; i++) {
      const float* a = &acc[8 * i];
      const uint32_t a0 = pack_bf16(a[0], a[1]), a1 = pack_bf16(a[2], a[3]), a2 = pack_bf16(a[4], a[5]), a3 = pack_bf16(a[6], a[7]);
#pragma unroll
      for (int jh = 0; jh < 2; jh++) {
        float y[4];
        mma16<false>(y, a0, a1, a2, a3, tc[2 * jh], tc[2 * jh + 1]);
        sts(sy[2 * i] + jh * (4 * 584 * 4), pack_bf16(y[0], y[1]));
        sts(sy[2 * i + 1] + jh * (4 * 584 * 4), pack_bf16(y[2], y[3]));
      }
    }
    if (wg == 2) bar_arrive(7, NTHR); else bar_sync(7, NTHR);
    if (wg) bar_sync(15, NTHR);
    if (wg < 2) {
      uint2 y[9], sh[9], sw[9];
#pragma unroll
      for (int i = 0; i < 9; i++) y[i] = lds2(syl + 256 * i);
      uint32_t sel = 0x5410, sto = sbase + O_B3 + wg * 9216;
#pragma unroll 1
      for (int e = 0; e < 2; e++, sel = 0x7632, sto += 4608) {
        float a[18];
#pragma unroll
        for (int i = 0; i < 9; i++) {
          const uint32_t x1 = hfma2(ga[i], __byte_perm(y[i].x, y[i].y, sel), xr[i]);
          xr[i] = xr[9 + i]; xr[9 + i] = x1;
          a[2 * i] = bf_lo(x1); a[2 * i + 1] = bf_hi(x1);
        }
#pragma unroll
        for (int i = 0; i < 9; i++) { lds2_if(!e, sh[i], l8 + sbase + O_MOD + 4 * D_ + 256 * i); lds2_if(!e, sw[i], l8 + sbase + O_MOD + 8 * D_ + 256 * i); }
        float oa, ra;
        ln_stats1(a, 1.0f, oa, ra);
#pragma unroll
        for (int i = 0; i < 9; i++) {
          a[2 * i] = fmaf(fmaf(a[2 * i], ra, oa), __uint_as_float(sw[i].x), __uint_as_float(sh[i].x));
          a[2 * i + 1] = fmaf(fmaf(a[2 * i + 1], ra, oa), __uint_as_float(sw[i].y), __uint_as_float(sh[i].y));
        }
        ln_stats1(a, 0.5f, oa, ra);
        uint32_t hv[9];
#pragma unroll
        for (int i = 0; i < 9; i++) hv[i] = bitsel(pack_bf16(fmaf(a[2 * i], ra, oa), fmaf(a[2 * i + 1], ra, oa)), ham[i == 2 ? 1 : i == 6 ? 2 : 0], tag1);
        if (!(wg | e)) {
          if (elect()) red_add(hh3, 1);
#pragma unroll
          for (int i = 0; i < 9; i++) asm volatile("st.global.b32 [%0], %1;" ::"l"(h3g + sh3[i == 2 ? 1 : i == 6 ? 2 : 0] + i * 8192), "r"(hv[i]) : "memory");
          bar_arrive(15, NTHR);
        } else {
#pragma unroll
          for (int i = 0; i < 9; i++) sts(sto + sh3[i == 2 ? 1 : i == 6 ? 2 : 0] + i * 512, hv[i]);
        }
        if (!e) bar_arrive(8, 288);
      }
      fence_async_smem();
      bar_arrive(9, 288);
    }
  }

  const bool g2 = rows;
  const int z2 = cta, r = z2 >> 6;
  const int s2 = 128 * ((z2 >> 2) & 15), d2 = 144 * (z2 & 3);
  constexpr int ST0 = 32 % NST;
  const bool first = helper || m1 < W0N;

  if (wg == 2) {
    asm volatile("setmaxnreg.dec.sync.aligned.u32 40;");
    const int l = lane_id(), g = l >> 2;
    auto load_b = [&](bool second, int i, int st) {
      const uint32_t lb = full0 + 8 * (B_LAND + st), bytes = second ? 18432 : STAGE - a1bytes;
      mbar_expect(lb, bytes);
      bulk_ld(sbase + (second ? st * STAGE2 + 16384 : st * STAGE + a1bytes),
              second ? sc->u + ((size_t)(36 * r + kb2_order(i)) * D_ + d2) * 128 : sc->h3 + ((size_t)(i * 18 + (d1 >> 5)) << 12), bytes, lb);
    };
    if (wp == 8) {
      int st = rows ? 4 : 0, ph = 1;
#pragma unroll 1
      for (int kb = st; kb < 32; kb++) {
        if (rows && (kb >> 1) == 2) mbar_wait(full0 + 8 * (B_S4 - 4 + kb), 0);
        mbar_wait(empty0 + 8 * st, ph);
        if (elect()) {
          load_a1(st, kb);
        }
        __syncwarp();
        ring_next<false>(st, ph);
      }
      if (g2) {
        st++;
#pragma unroll 1
        for (int i = 0; i < 36; i++) {
          if (i == HOLDA) mbar_wait(full0 + 8 * B_GO, 0);
          mbar_wait(empty0 + 8 * st, ph);
          if (elect()) {
            mbar_expect(full0 + 8 * st, 16384);
            tma3d_ef(sbase + st * STAGE2, &maps.w2, 64 * (36 * r + kb2_order(i)), s2 >> 6, full0 + 8 * st);
          }
          __syncwarp();
          ring_next<true>(st, ph);
        }
      }
    } else if (wp >= 10) {
      const int sw = wp - 10;
      if (sw) {
        if (rows) {
          bar_sync(8, 288);
          mbar_wait(full0, 0);
          if (elect()) mbar_arrive(full0 + 8 * B_S4);
          bar_sync(9, 288);
          if (elect()) tma_st3d(&maps.h3, sbase + O_B3 + 4608, 64 * (cta & 15), 18 * (cta >> 4), 1);
          bulk_commit_wait();
          if (elect()) {
            red_add(sc->cnt + C_H3 + (cta >> 4) + 8, 4);
            mbar_arrive(full0 + 8 * B_S5);
            asm volatile("fence.acq_rel.gpu;" ::: "memory");
            red_add(&sc->cnt[C_X + 64], 1);
          }
          __syncwarp();
        }
        if (g2) {
          sts(sbase + O_GB + 288 + 4 * l, ld_nc(p.b2 + s2 + 64 * (r ^ 1) + 2 * l));
          uint2 v[3];
          int it = 0;
          do {
#pragma unroll
            for (int i = 0; i < 3; i++) v[i] = ld_rlx2(sc->mod + 3 * D_ + d2 + 2 * min(l + 32 * i, 71));
          } while (any(or3(diff2(v[0].x, v[0].y, tag16), diff2(v[1].x, v[1].y, tag16), diff2(v[2].x, v[2].y, tag16)) & 0xffffu) && ++it < SPIN_MAX);
#pragma unroll
          for (int i = 0; i < 3; i++) sts(sbase + O_GB + 4 * min(l + 32 * i, 71), __byte_perm(v[i].x, v[i].y, 0x7632));
          __syncwarp();
        }
        wait_cnt<true>(&sc->cnt[C_X + 64], 128 * ep);
        if (elect()) mbar_arrive(full0 + 8 * B_X);
        __syncwarp();
      }
      uint32_t lph = 0;
      auto check_tiles = [&](bool second, int n, int st, uint32_t o1, uint32_t d2nd) {
        const uint32_t b1 = pin(sbase + o1), b2 = pin(sbase + o1 + d2nd);
        int i = 0, it = 0;
#pragma unroll 1
        do {
          const uint32_t so = st * (second ? STAGE2 : STAGE);
          mbar_wait(full0 + 8 * (B_LAND + st), (lph >> st) & 1);
          lph ^= 1u << st;
          uint32_t v[20];
#pragma unroll
          for (int k = 0; k < 20; k++) if (!second || k < 10 || k >= 12) v[k] = lds(k < 12 ? b1 + so + k * 1024 : b2 + so + (k - 12) * 1024); else v[k] = tag1;
#pragma unroll
          for (int k = 0; k < 10; k++) v[k] = diff2(v[2 * k], v[2 * k + 1], tag1);
          const uint32_t bad = or3(or3(or3(v[0], v[1], v[2]), or3(v[3], v[4], v[5]), v[6]), v[7], or3(v[8], v[9], 0));
          if (__builtin_expect(any(bad & 1) && ++it < SPIN_MAX, 0)) {
            fence_async_smem();
            __syncwarp();
            if (elect()) load_b(second, i, st);
            __syncwarp();
            continue;
          }
          if (elect()) mbar_arrive(full0 + 8 * st);
          if (++st == NST) st = 0;
          i++;
        } while (i < n);
      };
      if (!sw) check_tiles(false, NV1, 0, a1bytes + l * 32 + (l >> 2) * 4, helper ? 4096 : 12288);
      if (sw) {
#pragma unroll 1
        for (int k = 0; k < 2; k++) {
          bar_sync(13 + k, 160);
          if (helper || (first && !k)) continue;
          const uint32_t stg = sbase + (k ? O_U1 : ST0 * STAGE);
          const int kb = (f1 >> 6) + (k ^ flip);
          uint8_t* const ug = sc->u + ((size_t)kb * D_ + d1) * 128;
          if (g2) mbar_wait(full0 + 8 * B_GO, 0);
          if (first) pause(10 * TRK0);
#pragma unroll 1
          for (int i = 0; i < 20480; i += 2048) {
            if (elect()) bulk_st(ug + i, stg + i, 2048);
            pause(k ? TRKC : TRK0);
          }
          if (elect()) red_add(sc->cnt + C_U + kb2_pos(kb), 4);
          bulk_commit_wait();
          if (elect()) { if (!k) mbar_arrive(empty0 + 8 * ST0); }
          __syncwarp();
        }
        if (elect()) { asm volatile("fence.acq_rel.gpu;" ::: "memory"); red_add(&sc->cnt[C_X], 1); }
        __syncwarp();
      }
      if (g2) {
        if (!sw) check_tiles(true, NV2, 3, 16384 + l * 32 + g * 4, 10240);
        else {
          wait_cnt<true>(&sc->cnt[C_X], NCTA * ep);
          if (elect()) mbar_arrive(full0 + 8 * B_X);
          if (cta == 0) sc->cnt[C_EP + l] = ep;
          __syncwarp();
        }
      }
      __syncwarp();
    } else {
      uint32_t ready = 0;
      int st = 0, ph = 1;
#pragma unroll 1
      for (int kb = 0; kb < 32; kb++) {
        const uint8_t* src = upin(sc->h3 + ((size_t)(kb * 18 + (d1 >> 5)) << 12));
        const uint32_t dst = upin(sbase + st * STAGE + a1bytes), lb = full0 + 8 * ((kb < NV1 ? B_LAND : 0) + st);
        if (kb == NV1) { mbar_wait(full0 + 8 * B_X, 0); fence_async_glb(); ready = ~0u; }
        if (rows && (kb >> 1) == 2) mbar_wait(full0 + 8 * (B_S4 - 4 + kb), 0);
        mbar_wait(empty0 + 8 * st, ph);
        if (elect()) mbar_expect(lb, STAGE - a1bytes);
        wait_flags(sc->cnt + C_H3 + l, (kb & 7) + (kb < 8 ? 0 : 8), 64 * ep, ready);
        if (elect()) bulk_ld(dst, src, STAGE - a1bytes, lb);
        ring_next<false>(st, ph);
      }
      if (g2) {
        ready = 0;
        st++;
#pragma unroll 1
        for (int i = 0; i < 36; i++) {
          const int kb = kb2_order(i);
          const uint8_t* src = upin(sc->u + ((size_t)(36 * r + kb) * D_ + d2) * 128);
          const uint32_t dst = upin(sbase + st * STAGE2 + 16384), lb = full0 + 8 * ((i < NV2 ? B_LAND : 0) + st);
          if (i == NV2) { mbar_wait(full0 + 8 * B_X, 1); fence_async_glb(); ready = ~0u; }
          mbar_wait(empty0 + 8 * st, ph);
          if (elect()) mbar_expect(lb, 18432);
          wait_flags(sc->cnt + C_U + 64 * r + l, i & 31, 16 * ep, ready);
          if (elect()) {
            bulk_ld(dst, src, 18432, lb);
            if (i == 0) mbar_arrive(full0 + 8 * B_GO);
          }
          ring_next<true>(st, ph);
        }
      }
    }
  } else {
    asm volatile("setmaxnreg.inc.sync.aligned.u32 232;");
    const int wgu = wg;
    constexpr uint32_t sb4 = sbase >> 4;
    const int w = wp & 3;
    Ring rg = {0, 0};
    const int direct = helper || (first && !wg), kbA = (f1 >> 6) + (helper ? 2 : 1) * (wg ^ flip), kbB = (f1 >> 6) + 1;
    const int ud1 = helper ? (kbB - kbA) * (D_ * 128) - 3 * 4096 : 0;
    uint32_t ad, um0, um1, eh;
    uint8_t* ug0;
    unsigned* uh;
    auto side1 = [&]() {
      const int l = lane_id(), g = l >> 2, t = l & 3;
      if (rows) {
        uint32_t* const x1p = p.out + (size_t)(cta + 128 * (w + 8 * wg)) * 288 + l;
#pragma unroll
        for (int i = 0; i < 9; i++) { x1p[32 * i] = xr[i]; x1p[512 * 288 + 32 * i] = xr[9 + i]; }
      }
      const uint32_t uo = (t >> 1) * 2048 + (16 * w + g) * 32 + (((t ^ (g >> 2)) & 1) << 4);
      ad = sbase + (wg ? O_U1 : ST0 * STAGE) + uo;
      ug0 = sc->u + ((size_t)kbA * D_ + d1) * 128 + uo;
      uh = sc->cnt + C_U + kb2_pos(l ? kbB : kbA);
      eh = direct && !helper && !l;
      const bool utg = ((t ^ (g >> 2) ^ w) & 1) == 0;
      um0 = utg && g < 4 ? ~1u : ~0u; um1 = utg && g >= 4 ? ~1u : ~0u;
    };
    float acc[96];
    constexpr uint32_t LA = (8192 >> 4) << 16, LB = (4096 >> 4) << 16;
    {
      const float a0 = 0.5f * bf_lo(pin(bia[0])), a1 = 0.5f * bf_lo(pin(bia[1])), b0 = 0.5f * bf_lo(pin(bia[2])), b1 = 0.5f * bf_lo(pin(bia[3]));
#pragma unroll
      for (int i = 0; i < 96; i++) acc[i] = i < 48 ? ((i & 2) ? a1 : a0) : ((i & 2) ? b1 : b0);
      reg_fence(acc);
    }
    if (!helper) gemm_main<0>(acc, sb4 + (wgu ^ flip) * 512 + LA, 0, sb4 + 1024 + LB, wgu, rg, first ? NST : NST - 1, side1);
    else {
      float ac2[96];
#pragma unroll
      for (int i = 0; i < 96; i++) asm volatile("mov.b32 %0, %1;" : "=f"(ac2[i]) : "f"(acc[i]));
      gemm_main<1>(ac2, sb4 + (wgu ^ flip) * 1024 + LA, sb4 + 512 + LA, sb4 + 1536 + LB, wgu, rg, NST - 1, side1);
#pragma unroll
      for (int i = 0; i < 96; i++) asm volatile("mov.b32 %0, %1;" : "=f"(acc[i]) : "f"(ac2[i]));
    }
    {
      float tp[2] = {0.f, 0.f};
#pragma unroll
      for (int j = 0; j < 12; j++) {
        const float* a = &acc[16 * (j >> 1) + 2 * (j & 1)];
        const float k3 = j < 2 ? GK3 : fmaf(tp[j & 1], 0.0f, GK3);
        uint32_t o[4];
#pragma unroll
        for (int e = 0; e < 4; e++) {
          const float h0 = a[4 * e], h1 = a[4 * e + 1];
          float z0 = h0 * fmaf(h0 * k3, h0, GK1), z1 = h1 * fmaf(h1 * k3, h1, GK1);
          asm("tanh.approx.f32 %0, %0;" : "+f"(z0));
          asm("tanh.approx.f32 %0, %0;" : "+f"(z1));
          if (e == 3) tp[j & 1] = z0;
          o[e] = pack_bf16(fmaf(h0, z0, h0), fmaf(h1, z1, h1));
          if ((e >> 1) == (j & 1)) o[e] = bitsel(o[e], (e & 1) ? um1 : um0, tag1);
        }
        if (j == EH) asm volatile("{\n.reg .pred p;\nsetp.ne.u32 p, %1, 0;\n@p red.relaxed.gpu.global.add.u32 [%0], 1;\n}" ::"l"(uh), "r"(eh) : "memory");
        asm volatile("{\n.reg .pred p;\nsetp.ne.u32 p, %6, 0;\n@p st.global.v4.b32 [%0], {%2,%3,%4,%5};\n@!p st.shared.v4.b32 [%1], {%2,%3,%4,%5};\n}"
                     ::"l"(ug0 + (j < 6 ? 0 : ud1) + (j >> 1) * 4096 + (j & 1) * 256), "r"(ad + (j >> 1) * 4096 + (j & 1) * 256),
                       "r"(o[0]), "r"(o[1]), "r"(o[2]), "r"(o[3]), "r"(direct) : "memory");
        if ((j == 5 && helper && !wgu) || (j == 9 && !helper)) break;
      }
      if (!direct) fence_async_smem();
      else if (l <= wgu && helper) red_add(uh, 1);
      __syncwarp();
      bar_arrive(13 + wgu, 160);
    }
    if (g2) {
      const int mb = wgu ^ r;
      const int odd = z2 & 1;
      uint4 gq[4];
      uint2 gs;
      {
        float a0 = 0.f, a1 = 0.f;
        if (wgu) { a0 = lds_bf(sbase + O_GB + 288 + 2 * (16 * w + g)); a1 = lds_bf(sbase + O_GB + 288 + 16 + 2 * (16 * w + g)); }
#pragma unroll
        for (int i = 0; i < 4; i++) gq[i] = lds4(sbase + O_GB + 32 * odd + 64 * i + 16 * t);
        gs = lds2(sbase + O_GB + (odd ? 0 : 256) + 8 * t);
#pragma unroll
        for (int i = 0; i < 72; i++) acc[i] = (i & 2) ? a1 : a0;
      }
      uint32_t* const ob = p.out + (size_t)(s2 + 64 * mb + 16 * w + g) * 288 + (d2 >> 1);
      uint32_t* const oq = pin(ob + 8 * odd + 4 * t);
      uint32_t* const os = pin(ob + (odd ? 0 : 64) + 2 * t);
      rg.st++;
      gemm_main<3>(acc, sb4 + mb * 512 + LA, 0, sb4 + 1024 + ((2048 >> 4) << 16), wgu, rg, NST, []() {});
      auto finish = [&](const float* aq, const float* as) {
#pragma unroll
        for (int i = 0; i < 8; i++) {
          const float* a = aq + 16 * (i >> 1) + 2 * (i & 1);
          const uint4 gv = gq[i >> 1];
          red_bf16x8(oq + (i & 1) * 2304 + 16 * (i >> 1), hmul2(gv.x, pack_bf16(a[0], a[1])), hmul2(gv.y, pack_bf16(a[4], a[5])),
                     hmul2(gv.z, pack_bf16(a[8], a[9])), hmul2(gv.w, pack_bf16(a[12], a[13])));
        }
#pragma unroll
        for (int i = 0; i < 2; i++) red_bf16x4(os + i * 2304, hmul2(gs.x, pack_bf16(as[2 * i], as[2 * i + 1])), hmul2(gs.y, pack_bf16(as[2 * i + 4], as[2 * i + 5])));
      };
      if (odd) finish(&acc[8], &acc[0]); else finish(&acc[0], &acc[64]);
      __syncwarp();
    }
  }
}

typedef CUresult (*EncodeFn)(CUtensorMap*, CUtensorMapDataType, cuuint32_t, void*, const cuuint64_t*, const cuuint64_t*, const cuuint32_t*,
                             const cuuint32_t*, CUtensorMapInterleave, CUtensorMapSwizzle, CUtensorMapL2promotion, CUtensorMapFloatOOBfill);

struct Dim { cuuint64_t n, stride; cuuint32_t box; };
template <int RANK>
void make_map(EncodeFn enc, CUtensorMap* m, bool words, int swz, const void* ptr, const Dim (&d)[RANK]) {
  cuuint64_t gd[RANK], gs[RANK];
  cuuint32_t bx[RANK], es[RANK];
  for (int i = 0; i < RANK; i++) { gd[i] = d[i].n; gs[i] = d[i].stride; bx[i] = d[i].box; es[i] = 1; }
  enc(m, words ? CU_TENSOR_MAP_DATA_TYPE_UINT32 : CU_TENSOR_MAP_DATA_TYPE_BFLOAT16, RANK, const_cast<void*>(ptr), gd, gs + 1, bx, es,
      CU_TENSOR_MAP_INTERLEAVE_NONE, static_cast<CUtensorMapSwizzle>(swz),
      swz == 3 ? CU_TENSOR_MAP_L2_PROMOTION_L2_256B : CU_TENSOR_MAP_L2_PROMOTION_NONE, CU_TENSOR_MAP_FLOAT_OOB_FILL_NONE);
}

}

extern "C" void kernel_launch(void* const* d_in, const int* in_sizes, int n_in, void* d_out, int out_size) {
  (void)in_sizes; (void)n_in; (void)out_size;
  static EncodeFn enc = nullptr;
  static void *sptr = nullptr, *tptr = nullptr;
  if (!enc) {
    void* f = nullptr; cudaDriverEntryPointQueryResult qr;
    cudaGetDriverEntryPoint("cuTensorMapEncodeTiled", &f, cudaEnableDefault, &qr);
    enc = reinterpret_cast<EncodeFn>(f);
    cudaFuncSetAttribute(fused_kernel, cudaFuncAttributeMaxDynamicSharedMemorySize, SMEM_BYTES);
    cudaGetSymbolAddress(&sptr, g_s);
    cudaGetSymbolAddress(&tptr, T_TAB);
  }
  Params p;
  p.x = (const __nv_bfloat16*)d_in[0]; p.wr = (const __nv_bfloat16*)d_in[1]; p.wi = (const __nv_bfloat16*)d_in[2];
  p.b1 = (const __nv_bfloat16*)d_in[5]; p.b2 = (const __nv_bfloat16*)d_in[7];
  p.c = (const __nv_bfloat16*)d_in[8]; p.wmod = (const __nv_bfloat16*)d_in[9];
  p.w1 = (const __nv_bfloat16*)d_in[4]; p.w2 = (const __nv_bfloat16*)d_in[6];
  p.out = static_cast<uint32_t*>(d_out); p.s = static_cast<Scratch*>(sptr); p.tab = static_cast<const uint4*>(tptr);
  Maps maps;
  make_map<4>(enc, &maps.w1a, false, 3, p.w1, {{64, 0, 64}, {16, 128 * 2 * F_, 4}, {128, 2 * F_, 16}, {72, 128, 2}});
  make_map<4>(enc, &maps.w1b, false, 3, p.w1, {{64, 0, 64}, {16, 128 * 2 * F_, 4}, {128, 2 * F_, 16}, {72, 128, 3}});
  make_map<3>(enc, &maps.w2, false, 3, p.w2, {{64, 0, 64}, {F_, 2 * S_, 64}, {32, 128, 2}});
  make_map<2>(enc, &maps.z1, true, 0, p.s->z1, {{5120, 0, 40}, {120, 20480, 60}});
  for (int i = 0; i < 2; i++) make_map<2>(enc, &maps.z2[i], true, 0, p.s->z2, {{4800, 0, i ? 16u : 24u}, {128, 19200, 128}});
  for (int i = 0; i < 4; i++) make_map<2>(enc, &maps.wf[i], false, 2 - (i & 1), (i & 2) ? p.wi : p.wr, {{16 * DF_, 0, (i & 1) ? 16u : 32u}, {128, 32 * DF_, 128}});
  make_map<2>(enc, &maps.wm, false, 1, p.wmod, {{6 * D_, 0, 16}, {D_, 12 * D_, 192}});
  make_map<3>(enc, &maps.h3, true, 0, p.s->h3, {{1024, 0, 64}, {144, 4096, 18}, {4, 144 * 4096, 3}});
  fused_kernel<<<NCTA, NTHR, SMEM_BYTES, cudaStreamPerThread>>>(p, maps);
}
```

```cpp
#include <cuda_runtime.h>
#include <cuda_bf16.h>
#include <cuda.h>
#include <stdint.h>

namespace {

constexpr int S_ = 2048, D_ = 576, DF_ = 289, F_ = 4608;
constexpr int NCTA = 132, NTHR = 384;
constexpr int STAGE = 36864, NST = 6;
constexpr int STAGE2 = 34816, O_U1 = NST * STAGE2, O_GB = O_U1 + 20480, O_HALF = O_GB + 512, SMEM_BYTES = 232448;
constexpr uint32_t sbase = 1024, red = sbase + NST * STAGE, full0 = sbase + SMEM_BYTES - 256, empty0 = full0 + 8 * NST;
constexpr int O_NRM = 0, O_B1 = 19456, O_Z1 = 38912, O_P2 = 59392, O_ST = 3 * STAGE;
constexpr int O_RAW = 4 * STAGE;
constexpr int O_IN = 4 * STAGE, O_Y = O_IN + 19456, O_B3 = O_IN + 38912, O_MOD = O_IN + 57344;

__device__ __align__(128) const uint32_t T_TAB[5632] = {
0x3f803f80,0xbf803f80,0x3f803f80,0xbf803f80,0x3f803f80,0xbf803f80,0x3f803f80,0xbf803f80,0x3f803f80,0xbf803f80,0x3f803f80,0xbf803f80,
0x3f803f80,0xbf803f80,0x3f803f80,0xbf803f80,0x3f7f3f80,0xbdc90000,0x3f223f35,0xbf46bf35,0x3f753f7b,0xbe95be48,0x3ef13f0e,0xbf62bf55,
0x3f623f6d,0xbef1bec4,0x3e953ec4,0xbf75bf6d,0x3f463f55,0xbf22bf0e,0x3dc93e48,0xbf7fbf7b,0x3f7b3f80,0xbe480000,0xbe480000,0xbf7bbf80,
0x3f553f6d,0xbf0ebec4,0xbf0ebec4,0xbf55bf6d,0x3f0e3f35,0xbf55bf35,0xbf55bf35,0xbf0ebf35,0x3e483ec4,0xbf7bbf6d,0xbf7bbf6d,0xbe48bec4,
0x3f753f80,0xbe950000,0xbf62bf35,0xbef1bf35,0x3f223f55,0xbf46bf0e,0xbf7fbf7b,0x3dc9be48,0x3dc93ec4,0xbf7fbf6d,0xbf46bf6d,0x3f223ec4,
0xbef1be48,0xbf62bf7b,0xbe95bf0e,0x3f753f55,0x3f6d3f80,0xbec40000,0xbf6dbf80,0x3ec40000,0x3ec43f35,0xbf6dbf35,0xbec4bf35,0x3f6d3f35,
0xbec40000,0xbf6dbf80,0x3ec40000,0x3f6d3f80,0xbf6dbf35,0xbec4bf35,0x3f6d3f35,0x3ec43f35,0x3f623f80,0xbef10000,0xbe95bf35,0x3f753f35,
0x3dc93f0e,0xbf7fbf55,0x3f223e48,0x3f463f7b,0xbf46bec4,0xbf22bf6d,0x3f7f3f6d,0xbdc93ec4,0xbf75bf7b,0x3e95be48,0x3ef13f55,0xbf62bf0e,
0x3f553f80,0xbf0e0000,0x3f0e0000,0x3f553f80,0xbe483ec4,0xbf7bbf6d,0x3f7b3f6d,0xbe483ec4,0xbf7bbf35,0xbe48bf35,0x3e483f35,0xbf7bbf35,
0xbf0ebf6d,0x3f553ec4,0xbf55bec4,0xbf0ebf6d,0x3f463f80,0xbf220000,0x3f7f3f35,0x3dc93f35,0xbef13e48,0xbf62bf7b,0x3e953f55,0xbf75bf0e,
0xbf75bf6d,0x3e95bec4,0xbf62bec4,0xbef1bf6d,0x3dc9bf0e,0x3f7f3f55,0xbf22bf7b,0x3f463e48,0x3f353f80,0xbf350000,0x3f353f80,0xbf350000,
0xbf350000,0xbf35bf80,0xbf350000,0xbf35bf80,0xbf35bf80,0x3f350000,0xbf35bf80,0x3f350000,0x3f350000,0x3f353f80,0x3f350000,0x3f353f80,
0x3f223f80,0xbf460000,0xbdc93f35,0xbf7fbf35,0xbf62be48,0xbef1bf7b,0xbf75bf55,0x3e95bf0e,0xbe95bf6d,0x3f753ec4,0x3ef1bec4,0x3f623f6d,
0x3f7f3f0e,0x3dc93f55,0x3f463f7b,0xbf223e48,0x3f0e3f80,0xbf550000,0xbf550000,0xbf0ebf80,0xbf7bbec4,0xbe48bf6d,0xbe48bf6d,0x3f7b3ec4,
0x3e48bf35,0x3f7b3f35,0x3f7b3f35,0xbe483f35,0x3f553f6d,0xbf0e3ec4,0xbf0e3ec4,0xbf55bf6d,0x3ef13f80,0xbf620000,0xbf75bf35,0x3e95bf35,
0xbf7fbf0e,0x3dc9bf55,0x3f46be48,0x3f223f7b,0x3f22bec4,0x3f463f6d,0x3dc93f6d,0xbf7fbec4,0x3e953f7b,0xbf75be48,0xbf62bf55,0x3ef1bf0e,
0x3ec43f80,0xbf6d0000,0xbec4bf80,0x3f6d0000,0xbf6dbf35,0x3ec4bf35,0x3f6d3f35,0xbec43f35,0x3f6d0000,0x3ec43f80,0xbf6d0000,0xbec4bf80,
0xbec43f35,0xbf6dbf35,0x3ec4bf35,0x3f6d3f35,0x3e953f80,0xbf750000,0x3ef1bf35,0x3f623f35,0xbf46bf55,0x3f22bf0e,0x3dc93f7b,0xbf7fbe48,
0x3f7f3ec4,0xbdc93f6d,0xbf22bf6d,0x3f46bec4,0xbf623e48,0xbef1bf7b,0x3f753f0e,0xbe953f55,0x3e483f80,0xbf7b0000,0x3f7b0000,0x3e483f80,
0xbf0ebf6d,0x3f55bec4,0xbf553ec4,0xbf0ebf6d,0x3f553f35,0xbf0e3f35,0x3f0ebf35,0x3f553f35,0xbf7bbec4,0x3e48bf6d,0xbe483f6d,0xbf7bbec4,
0x3dc93f80,0xbf7f0000,0x3f463f35,0xbf223f35,0xbe95bf7b,0x3f75be48,0xbf62bf0e,0x3ef1bf55,0x3ef13f6d,0xbf623ec4,0x3f753ec4,0xbe953f6d,
0xbf22bf55,0x3f46bf0e,0xbf7fbe48,0x3dc9bf7b,0x3f80,0xbf800000,0x3f80,0xbf800000,0xbf80,0x3f800000,0xbf80,0x3f800000,
0x3f80,0xbf800000,0x3f80,0xbf800000,0xbf80,0x3f800000,0xbf80,0x3f800000,0xbdc93f80,0xbf7f0000,0xbf463f35,0xbf22bf35,
0x3e95bf7b,0x3f753e48,0x3f62bf0e,0x3ef13f55,0xbef13f6d,0xbf62bec4,0xbf753ec4,0xbe95bf6d,0x3f22bf55,0x3f463f0e,0x3f7fbe48,0x3dc93f7b,
0xbe483f80,0xbf7b0000,0xbf7b0000,0x3e48bf80,0x3f0ebf6d,0x3f553ec4,0x3f553ec4,0xbf0e3f6d,0xbf553f35,0xbf0ebf35,0xbf0ebf35,0x3f55bf35,
0x3f7bbec4,0x3e483f6d,0x3e483f6d,0xbf7b3ec4,0xbe953f80,0xbf750000,0xbef1bf35,0x3f62bf35,0x3f46bf55,0x3f223f0e,0xbdc93f7b,0xbf7f3e48,
0xbf7f3ec4,0xbdc9bf6d,0x3f22bf6d,0x3f463ec4,0x3f623e48,0xbef13f7b,0xbf753f0e,0xbe95bf55,0xbec43f80,0xbf6d0000,0x3ec4bf80,0x3f6d0000,
0x3f6dbf35,0x3ec43f35,0xbf6d3f35,0xbec4bf35,0xbf6d0000,0x3ec4bf80,0x3f6d0000,0xbec43f80,0x3ec43f35,0xbf6d3f35,0xbec4bf35,0x3f6dbf35,
0xbef13f80,0xbf620000,0x3f75bf35,0x3e953f35,0x3f7fbf0e,0x3dc93f55,0xbf46be48,0x3f22bf7b,0xbf22bec4,0x3f46bf6d,0xbdc93f6d,0xbf7f3ec4,
0xbe953f7b,0xbf753e48,0x3f62bf55,0x3ef13f0e,0xbf0e3f80,0xbf550000,0x3f550000,0xbf0e3f80,0x3f7bbec4,0xbe483f6d,0x3e48bf6d,0x3f7bbec4,
0xbe48bf35,0x3f7bbf35,0xbf7b3f35,0xbe48bf35,0xbf553f6d,0xbf0ebec4,0x3f0e3ec4,0xbf553f6d,0xbf223f80,0xbf460000,0x3dc93f35,0xbf7f3f35,
0x3f62be48,0xbef13f7b,0x3f75bf55,0x3e953f0e,0x3e95bf6d,0x3f75bec4,0xbef1bec4,0x3f62bf6d,0xbf7f3f0e,0x3dc9bf55,0xbf463f7b,0xbf22be48,
0xbf353f80,0xbf350000,0xbf353f80,0xbf350000,0x3f350000,0xbf353f80,0x3f350000,0xbf353f80,0x3f35bf80,0x3f350000,0x3f35bf80,0x3f350000,
0xbf350000,0x3f35bf80,0xbf350000,0x3f35bf80,0xbf463f80,0xbf220000,0xbf7f3f35,0x3dc9bf35,0x3ef13e48,0xbf623f7b,0xbe953f55,0xbf753f0e,
0x3f75bf6d,0x3e953ec4,0x3f62bec4,0xbef13f6d,0xbdc9bf0e,0x3f7fbf55,0x3f22bf7b,0x3f46be48,0xbf553f80,0xbf0e0000,0xbf0e0000,0x3f55bf80,
0x3e483ec4,0xbf7b3f6d,0xbf7b3f6d,0xbe48bec4,0x3f7bbf35,0xbe483f35,0xbe483f35,0xbf7b3f35,0x3f0ebf6d,0x3f55bec4,0x3f55bec4,0xbf0e3f6d,
0xbf623f80,0xbef10000,0x3e95bf35,0x3f75bf35,0xbdc93f0e,0xbf7f3f55,0xbf223e48,0x3f46bf7b,0x3f46bec4,0xbf223f6d,0xbf7f3f6d,0xbdc9bec4,
0x3f75bf7b,0x3e953e48,0xbef13f55,0xbf623f0e,0xbf6d3f80,0xbec40000,0x3f6dbf80,0x3ec40000,0xbec43f35,0xbf6d3f35,0x3ec4bf35,0x3f6dbf35,
0x3ec40000,0xbf6d3f80,0xbec40000,0x3f6dbf80,0x3f6dbf35,0xbec43f35,0xbf6d3f35,0x3ec4bf35,0xbf753f80,0xbe950000,0x3f62bf35,0xbef13f35,
0xbf223f55,0xbf463f0e,0x3f7fbf7b,0x3dc93e48,0xbdc93ec4,0xbf7f3f6d,0x3f46bf6d,0x3f22bec4,0x3ef1be48,0xbf623f7b,0x3e95bf0e,0x3f75bf55,
0xbf7b3f80,0xbe480000,0x3e480000,0xbf7b3f80,0xbf553f6d,0xbf0e3ec4,0x3f0ebec4,0xbf553f6d,0xbf0e3f35,0xbf553f35,0x3f55bf35,0xbf0e3f35,
0xbe483ec4,0xbf7b3f6d,0x3f7bbf6d,0xbe483ec4,0xbf7f3f80,0xbdc90000,0xbf223f35,0xbf463f35,0xbf753f7b,0xbe953e48,0xbef13f0e,0xbf623f55,
0xbf623f6d,0xbef13ec4,0xbe953ec4,0xbf753f6d,0xbf463f55,0xbf223f0e,0xbdc93e48,0xbf7f3f7b,0x3f803f80,0xbf803f80,0x3f803f80,0xbf803f80,
0x3f803f80,0xbf803f80,0x3f803f80,0xbf803f80,0x3f803f80,0xbf803f80,0x3f803f80,0xbf803f80,0x3f803f80,0xbf803f80,0x3f803f80,0xbf803f80,
0xbdc90000,0xbf7fbf80,0xbf46bf35,0xbf22bf35,0xbe95be48,0xbf75bf7b,0xbf62bf55,0xbef1bf0e,0xbef1bec4,0xbf62bf6d,0xbf75bf6d,0xbe95bec4,
0xbf22bf0e,0xbf46bf55,0xbf7fbf7b,0xbdc9be48,0xbf7bbf80,0x3e480000,0x3e480000,0x3f7b3f80,0xbf55bf6d,0x3f0e3ec4,0x3f0e3ec4,0x3f553f6d,
0xbf0ebf35,0x3f553f35,0x3f553f35,0x3f0e3f35,0xbe48bec4,0x3f7b3f6d,0x3f7b3f6d,0x3e483ec4,0x3e950000,0x3f753f80,0x3ef13f35,0xbf62bf35,
0x3f463f0e,0x3f223f55,0xbdc93e48,0xbf7fbf7b,0x3f7f3f6d,0x3dc93ec4,0xbf22bec4,0xbf46bf6d,0x3f623f7b,0xbef1be48,0xbf75bf55,0xbe95bf0e,
0x3f6d3f80,0xbec40000,0xbf6dbf80,0x3ec40000,0x3ec43f35,0xbf6dbf35,0xbec4bf35,0x3f6d3f35,0xbec40000,0xbf6dbf80,0x3ec40000,0x3f6d3f80,
0xbf6dbf35,0xbec4bf35,0x3f6d3f35,0x3ec43f35,0xbef10000,0xbf62bf80,0x3f753f35,0x3e953f35,0xbf7fbf55,0xbdc9bf0e,0x3f463f7b,0xbf22be48,
0xbf22bf6d,0x3f463ec4,0xbdc93ec4,0xbf7fbf6d,0x3e95be48,0x3f753f7b,0xbf62bf0e,0xbef1bf55,0xbf55bf80,0x3f0e0000,0xbf0e0000,0xbf55bf80,
0x3e48bec4,0x3f7b3f6d,0xbf7bbf6d,0x3e48bec4,0x3f7b3f35,0x3e483f35,0xbe48bf35,0x3f7b3f35,0x3f0e3f6d,0xbf55bec4,0x3f553ec4,0x3f0e3f6d,
0x3f220000,0x3f463f80,0xbdc9bf35,0x3f7f3f35,0x3f623f7b,0xbef13e48,0x3f753f0e,0x3e953f55,0xbe953ec4,0xbf75bf6d,0x3ef13f6d,0xbf62bec4,
0xbf7fbf55,0x3dc9bf0e,0xbf46be48,0xbf22bf7b,0x3f353f80,0xbf350000,0x3f353f80,0xbf350000,0xbf350000,0xbf35bf80,0xbf350000,0xbf35bf80,
0xbf35bf80,0x3f350000,0xbf35bf80,0x3f350000,0x3f350000,0x3f353f80,0x3f350000,0x3f353f80,0xbf460000,0xbf22bf80,0xbf7fbf35,0x3dc9bf35,
0xbef1bf7b,0x3f623e48,0x3e95bf0e,0x3f753f55,0x3f753ec4,0x3e953f6d,0x3f623f6d,0xbef13ec4,0x3dc93f55,0xbf7fbf0e,0xbf223e48,0xbf46bf7b,
0xbf0ebf80,0x3f550000,0x3f550000,0x3f0e3f80,0x3f7b3ec4,0x3e483f6d,0x3e483f6d,0xbf7bbec4,0xbe483f35,0xbf7bbf35,0xbf7bbf35,0x3e48bf35,
0xbf55bf6d,0x3f0ebec4,0x3f0ebec4,0x3f553f6d,0x3f620000,0x3ef13f80,0xbe953f35,0xbf75bf35,0xbdc93f55,0xbf7fbf0e,0xbf22bf7b,0x3f46be48,
0xbf46bf6d,0x3f22bec4,0x3f7f3ec4,0x3dc93f6d,0x3f753e48,0x3e953f7b,0xbef13f0e,0xbf62bf55,0x3ec43f80,0xbf6d0000,0xbec4bf80,0x3f6d0000,
0xbf6dbf35,0x3ec4bf35,0x3f6d3f35,0xbec43f35,0x3f6d0000,0x3ec43f80,0xbf6d0000,0xbec4bf80,0xbec43f35,0xbf6dbf35,0x3ec4bf35,0x3f6d3f35,
0xbf750000,0xbe95bf80,0x3f623f35,0xbef13f35,0x3f22bf0e,0x3f463f55,0xbf7fbe48,0xbdc9bf7b,0xbdc93f6d,0xbf7fbec4,0x3f46bec4,0x3f223f6d,
0xbef1bf7b,0x3f62be48,0xbe953f55,0xbf75bf0e,0xbe48bf80,0x3f7b0000,0xbf7b0000,0xbe48bf80,0x3f0e3f6d,0xbf553ec4,0x3f55bec4,0x3f0e3f6d,
0xbf55bf35,0x3f0ebf35,0xbf0e3f35,0xbf55bf35,0x3f7b3ec4,0xbe483f6d,0x3e48bf6d,0x3f7b3ec4,0x3f7f0000,0x3dc93f80,0x3f22bf35,0x3f463f35,
0xbf753e48,0xbe95bf7b,0xbef13f55,0xbf62bf0e,0x3f62bec4,0x3ef13f6d,0x3e95bf6d,0x3f753ec4,0xbf463f0e,0xbf22bf55,0xbdc93f7b,0xbf7fbe48,
0x3f80,0xbf800000,0x3f80,0xbf800000,0xbf80,0x3f800000,0xbf80,0x3f800000,0x3f80,0xbf800000,0x3f80,0xbf800000,
0xbf80,0x3f800000,0xbf80,0x3f800000,0xbf7f0000,0x3dc9bf80,0xbf22bf35,0x3f46bf35,0x3f753e48,0xbe953f7b,0x3ef13f55,0xbf623f0e,
0xbf62bec4,0x3ef1bf6d,0xbe95bf6d,0x3f75bec4,0x3f463f0e,0xbf223f55,0x3dc93f7b,0xbf7f3e48,0x3e48bf80,0x3f7b0000,0x3f7b0000,0xbe483f80,
0xbf0e3f6d,0xbf55bec4,0xbf55bec4,0x3f0ebf6d,0x3f55bf35,0x3f0e3f35,0x3f0e3f35,0xbf553f35,0xbf7b3ec4,0xbe48bf6d,0xbe48bf6d,0x3f7bbec4,
0x3f750000,0xbe953f80,0xbf623f35,0xbef1bf35,0xbf22bf0e,0x3f46bf55,0x3f7fbe48,0xbdc93f7b,0x3dc93f6d,0xbf7f3ec4,0xbf46bec4,0x3f22bf6d,
0x3ef1bf7b,0x3f623e48,0x3e953f55,0xbf753f0e,0xbec43f80,0xbf6d0000,0x3ec4bf80,0x3f6d0000,0x3f6dbf35,0x3ec43f35,0xbf6d3f35,0xbec4bf35,
0xbf6d0000,0x3ec4bf80,0x3f6d0000,0xbec43f80,0x3ec43f35,0xbf6d3f35,0xbec4bf35,0x3f6dbf35,0xbf620000,0x3ef1bf80,0x3e953f35,0xbf753f35,
0x3dc93f55,0xbf7f3f0e,0x3f22bf7b,0x3f463e48,0x3f46bf6d,0x3f223ec4,0xbf7f3ec4,0x3dc9bf6d,0xbf753e48,0x3e95bf7b,0x3ef13f0e,0xbf623f55,
0x3f0ebf80,0x3f550000,0xbf550000,0x3f0ebf80,0xbf7b3ec4,0x3e48bf6d,0xbe483f6d,0xbf7b3ec4,0x3e483f35,0xbf7b3f35,0x3f7bbf35,0x3e483f35,
0x3f55bf6d,0x3f0e3ec4,0xbf0ebec4,0x3f55bf6d,0x3f460000,0xbf223f80,0x3f7fbf35,0x3dc93f35,0x3ef1bf7b,0x3f62be48,0xbe95bf0e,0x3f75bf55,
0xbf753ec4,0x3e95bf6d,0xbf623f6d,0xbef1bec4,0xbdc93f55,0xbf7f3f0e,0x3f223e48,0xbf463f7b,0xbf353f80,0xbf350000,0xbf353f80,0xbf350000,
0x3f350000,0xbf353f80,0x3f350000,0xbf353f80,0x3f35bf80,0x3f350000,0x3f35bf80,0x3f350000,0xbf350000,0x3f35bf80,0xbf350000,0x3f35bf80,
0xbf220000,0x3f46bf80,0x3dc9bf35,0x3f7fbf35,0xbf623f7b,0xbef1be48,0xbf753f0e,0x3e95bf55,0x3e953ec4,0xbf753f6d,0xbef13f6d,0xbf623ec4,
0x3f7fbf55,0x3dc93f0e,0x3f46be48,0xbf223f7b,0x3f55bf80,0x3f0e0000,0x3f0e0000,0xbf553f80,0xbe48bec4,0x3f7bbf6d,0x3f7bbf6d,0x3e483ec4,
0xbf7b3f35,0x3e48bf35,0x3e48bf35,0x3f7bbf35,0xbf0e3f6d,0xbf553ec4,0xbf553ec4,0x3f0ebf6d,0x3ef10000,0xbf623f80,0xbf753f35,0x3e95bf35,
0x3f7fbf55,0xbdc93f0e,0xbf463f7b,0xbf223e48,0x3f22bf6d,0x3f46bec4,0x3dc93ec4,0xbf7f3f6d,0xbe95be48,0x3f75bf7b,0x3f62bf0e,0xbef13f55,
0xbf6d3f80,0xbec40000,0x3f6dbf80,0x3ec40000,0xbec43f35,0xbf6d3f35,0x3ec4bf35,0x3f6dbf35,0x3ec40000,0xbf6d3f80,0xbec40000,0x3f6dbf80,
0x3f6dbf35,0xbec43f35,0xbf6d3f35,0x3ec4bf35,0xbe950000,0x3f75bf80,0xbef13f35,0xbf623f35,0xbf463f0e,0x3f22bf55,0x3dc93e48,0xbf7f3f7b,
0xbf7f3f6d,0x3dc9bec4,0x3f22bec4,0xbf463f6d,0xbf623f7b,0xbef13e48,0x3f75bf55,0xbe953f0e,0x3f7bbf80,0x3e480000,0xbe480000,0x3f7bbf80,
0x3f55bf6d,0x3f0ebec4,0xbf0e3ec4,0x3f55bf6d,0x3f0ebf35,0x3f55bf35,0xbf553f35,0x3f0ebf35,0x3e48bec4,0x3f7bbf6d,0xbf7b3f6d,0x3e48bec4,
0x3dc90000,0xbf7f3f80,0x3f46bf35,0xbf223f35,0x3e95be48,0xbf753f7b,0x3f62bf55,0xbef13f0e,0x3ef1bec4,0xbf623f6d,0x3f75bf6d,0xbe953ec4,
0x3f22bf0e,0xbf463f55,0x3f7fbf7b,0xbdc93e48,0x3f803f80,0xbf803f80,0x3f803f80,0xbf803f80,0x3f803f80,0xbf803f80,0x3f803f80,0xbf803f80,
0x3f803f80,0xbf803f80,0x3f803f80,0xbf803f80,0x3f803f80,0xbf803f80,0x3f803f80,0xbf803f80,0xbf7fbf80,0x3dc90000,0xbf22bf35,0x3f463f35,
0xbf75bf7b,0x3e953e48,0xbef1bf0e,0x3f623f55,0xbf62bf6d,0x3ef13ec4,0xbe95bec4,0x3f753f6d,0xbf46bf55,0x3f223f0e,0xbdc9be48,0x3f7f3f7b,
0x3f7b3f80,0xbe480000,0xbe480000,0xbf7bbf80,0x3f553f6d,0xbf0ebec4,0xbf0ebec4,0xbf55bf6d,0x3f0e3f35,0xbf55bf35,0xbf55bf35,0xbf0ebf35,
0x3e483ec4,0xbf7bbf6d,0xbf7bbf6d,0xbe48bec4,0xbf75bf80,0x3e950000,0x3f623f35,0x3ef13f35,0xbf22bf55,0x3f463f0e,0x3f7f3f7b,0xbdc93e48,
0xbdc9bec4,0x3f7f3f6d,0x3f463f6d,0xbf22bec4,0x3ef13e48,0x3f623f7b,0x3e953f0e,0xbf75bf55,0x3f6d3f80,0xbec40000,0xbf6dbf80,0x3ec40000,
0x3ec43f35,0xbf6dbf35,0xbec4bf35,0x3f6d3f35,0xbec40000,0xbf6dbf80,0x3ec40000,0x3f6d3f80,0xbf6dbf35,0xbec4bf35,0x3f6d3f35,0x3ec43f35,
0xbf62bf80,0x3ef10000,0x3e953f35,0xbf75bf35,0xbdc9bf0e,0x3f7f3f55,0xbf22be48,0xbf46bf7b,0x3f463ec4,0x3f223f6d,0xbf7fbf6d,0x3dc9bec4,
0x3f753f7b,0xbe953e48,0xbef1bf55,0x3f623f0e,0x3f553f80,0xbf0e0000,0x3f0e0000,0x3f553f80,0xbe483ec4,0xbf7bbf6d,0x3f7b3f6d,0xbe483ec4,
0xbf7bbf35,0xbe48bf35,0x3e483f35,0xbf7bbf35,0xbf0ebf6d,0x3f553ec4,0xbf55bec4,0xbf0ebf6d,0xbf46bf80,0x3f220000,0xbf7fbf35,0xbdc9bf35,
0x3ef1be48,0x3f623f7b,0xbe95bf55,0x3f753f0e,0x3f753f6d,0xbe953ec4,0x3f623ec4,0x3ef13f6d,0xbdc93f0e,0xbf7fbf55,0x3f223f7b,0xbf46be48,
0x3f353f80,0xbf350000,0x3f353f80,0xbf350000,0xbf350000,0xbf35bf80,0xbf350000,0xbf35bf80,0xbf35bf80,0x3f350000,0xbf35bf80,0x3f350000,
0x3f350000,0x3f353f80,0x3f350000,0x3f353f80,0xbf22bf80,0x3f460000,0x3dc9bf35,0x3f7f3f35,0x3f623e48,0x3ef13f7b,0x3f753f55,0xbe953f0e,
0x3e953f6d,0xbf75bec4,0xbef13ec4,0xbf62bf6d,0xbf7fbf0e,0xbdc9bf55,0xbf46bf7b,0x3f22be48,0x3f0e3f80,0xbf550000,0xbf550000,0xbf0ebf80,
0xbf7bbec4,0xbe48bf6d,0xbe48bf6d,0x3f7b3ec4,0x3e48bf35,0x3f7b3f35,0x3f7b3f35,0xbe483f35,0x3f553f6d,0xbf0e3ec4,0xbf0e3ec4,0xbf55bf6d,
0xbef1bf80,0x3f620000,0x3f753f35,0xbe953f35,0x3f7f3f0e,0xbdc93f55,0xbf463e48,0xbf22bf7b,0xbf223ec4,0xbf46bf6d,0xbdc9bf6d,0x3f7f3ec4,
0xbe95bf7b,0x3f753e48,0x3f623f55,0xbef13f0e,0x3ec43f80,0xbf6d0000,0xbec4bf80,0x3f6d0000,0xbf6dbf35,0x3ec4bf35,0x3f6d3f35,0xbec43f35,
0x3f6d0000,0x3ec43f80,0xbf6d0000,0xbec4bf80,0xbec43f35,0xbf6dbf35,0x3ec4bf35,0x3f6d3f35,0xbe95bf80,0x3f750000,0xbef13f35,0xbf62bf35,
0x3f463f55,0xbf223f0e,0xbdc9bf7b,0x3f7f3e48,0xbf7fbec4,0x3dc9bf6d,0x3f223f6d,0xbf463ec4,0x3f62be48,0x3ef13f7b,0xbf75bf0e,0x3e95bf55,
0x3e483f80,0xbf7b0000,0x3f7b0000,0x3e483f80,0xbf0ebf6d,0x3f55bec4,0xbf553ec4,0xbf0ebf6d,0x3f553f35,0xbf0e3f35,0x3f0ebf35,0x3f553f35,
0xbf7bbec4,0x3e48bf6d,0xbe483f6d,0xbf7bbec4,0xbdc9bf80,0x3f7f0000,0xbf46bf35,0x3f22bf35,0x3e953f7b,0xbf753e48,0x3f623f0e,0xbef13f55,
0xbef1bf6d,0x3f62bec4,0xbf75bec4,0x3e95bf6d,0x3f223f55,0xbf463f0e,0x3f7f3e48,0xbdc93f7b,0x3f80,0xbf800000,0x3f80,0xbf800000,
0xbf80,0x3f800000,0xbf80,0x3f800000,0x3f80,0xbf800000,0x3f80,0xbf800000,0xbf80,0x3f800000,0xbf80,0x3f800000,
0x3dc9bf80,0x3f7f0000,0x3f46bf35,0x3f223f35,0xbe953f7b,0xbf75be48,0xbf623f0e,0xbef1bf55,0x3ef1bf6d,0x3f623ec4,0x3f75bec4,0x3e953f6d,
0xbf223f55,0xbf46bf0e,0xbf7f3e48,0xbdc9bf7b,0xbe483f80,0xbf7b0000,0xbf7b0000,0x3e48bf80,0x3f0ebf6d,0x3f553ec4,0x3f553ec4,0xbf0e3f6d,
0xbf553f35,0xbf0ebf35,0xbf0ebf35,0x3f55bf35,0x3f7bbec4,0x3e483f6d,0x3e483f6d,0xbf7b3ec4,0x3e95bf80,0x3f750000,0x3ef13f35,0xbf623f35,
0xbf463f55,0xbf22bf0e,0x3dc9bf7b,0x3f7fbe48,0x3f7fbec4,0x3dc93f6d,0xbf223f6d,0xbf46bec4,0xbf62be48,0x3ef1bf7b,0x3f75bf0e,0x3e953f55,
0xbec43f80,0xbf6d0000,0x3ec4bf80,0x3f6d0000,0x3f6dbf35,0x3ec43f35,0xbf6d3f35,0xbec4bf35,0xbf6d0000,0x3ec4bf80,0x3f6d0000,0xbec43f80,
0x3ec43f35,0xbf6d3f35,0xbec4bf35,0x3f6dbf35,0x3ef1bf80,0x3f620000,0xbf753f35,0xbe95bf35,0xbf7f3f0e,0xbdc9bf55,0x3f463e48,0xbf223f7b,
0x3f223ec4,0xbf463f6d,0x3dc9bf6d,0x3f7fbec4,0x3e95bf7b,0x3f75be48,0xbf623f55,0xbef1bf0e,0xbf0e3f80,0xbf550000,0x3f550000,0xbf0e3f80,
0x3f7bbec4,0xbe483f6d,0x3e48bf6d,0x3f7bbec4,0xbe48bf35,0x3f7bbf35,0xbf7b3f35,0xbe48bf35,0xbf553f6d,0xbf0ebec4,0x3f0e3ec4,0xbf553f6d,
0x3f22bf80,0x3f460000,0xbdc9bf35,0x3f7fbf35,0xbf623e48,0x3ef1bf7b,0xbf753f55,0xbe95bf0e,0xbe953f6d,0xbf753ec4,0x3ef13ec4,0xbf623f6d,
0x3f7fbf0e,0xbdc93f55,0x3f46bf7b,0x3f223e48,0xbf353f80,0xbf350000,0xbf353f80,0xbf350000,0x3f350000,0xbf353f80,0x3f350000,0xbf353f80,
0x3f35bf80,0x3f350000,0x3f35bf80,0x3f350000,0xbf350000,0x3f35bf80,0xbf350000,0x3f35bf80,0x3f46bf80,0x3f220000,0x3f7fbf35,0xbdc93f35,
0xbef1be48,0x3f62bf7b,0x3e95bf55,0x3f75bf0e,0xbf753f6d,0xbe95bec4,0xbf623ec4,0x3ef1bf6d,0x3dc93f0e,0xbf7f3f55,0xbf223f7b,0xbf463e48,
0xbf553f80,0xbf0e0000,0xbf0e0000,0x3f55bf80,0x3e483ec4,0xbf7b3f6d,0xbf7b3f6d,0xbe48bec4,0x3f7bbf35,0xbe483f35,0xbe483f35,0xbf7b3f35,
0x3f0ebf6d,0x3f55bec4,0x3f55bec4,0xbf0e3f6d,0x3f62bf80,0x3ef10000,0xbe953f35,0xbf753f35,0x3dc9bf0e,0x3f7fbf55,0x3f22be48,0xbf463f7b,
0xbf463ec4,0x3f22bf6d,0x3f7fbf6d,0x3dc93ec4,0xbf753f7b,0xbe95be48,0x3ef1bf55,0x3f62bf0e,0xbf6d3f80,0xbec40000,0x3f6dbf80,0x3ec40000,
0xbec43f35,0xbf6d3f35,0x3ec4bf35,0x3f6dbf35,0x3ec40000,0xbf6d3f80,0xbec40000,0x3f6dbf80,0x3f6dbf35,0xbec43f35,0xbf6d3f35,0x3ec4bf35,
0x3f75bf80,0x3e950000,0xbf623f35,0x3ef1bf35,0x3f22bf55,0x3f46bf0e,0xbf7f3f7b,0xbdc9be48,0x3dc9bec4,0x3f7fbf6d,0xbf463f6d,0xbf223ec4,
0xbef13e48,0x3f62bf7b,0xbe953f0e,0xbf753f55,0xbf7b3f80,0xbe480000,0x3e480000,0xbf7b3f80,0xbf553f6d,0xbf0e3ec4,0x3f0ebec4,0xbf553f6d,
0xbf0e3f35,0xbf553f35,0x3f55bf35,0xbf0e3f35,0xbe483ec4,0xbf7b3f6d,0x3f7bbf6d,0xbe483ec4,0x3f7fbf80,0x3dc90000,0x3f22bf35,0x3f46bf35,
0x3f75bf7b,0x3e95be48,0x3ef1bf0e,0x3f62bf55,0x3f62bf6d,0x3ef1bec4,0x3e95bec4,0x3f75bf6d,0x3f46bf55,0x3f22bf0e,0x3dc9be48,0x3f7fbf7b,
0x3f803f80,0xbf803f80,0x3f803f80,0xbf803f80,0x3f803f80,0xbf803f80,0x3f803f80,0xbf803f80,0x3f803f80,0xbf803f80,0x3f803f80,0xbf803f80,
0x3f803f80,0xbf803f80,0x3f803f80,0xbf803f80,0x3dc90000,0x3f7f3f80,0x3f463f35,0x3f223f35,0x3e953e48,0x3f753f7b,0x3f623f55,0x3ef13f0e,
0x3ef13ec4,0x3f623f6d,0x3f753f6d,0x3e953ec4,0x3f223f0e,0x3f463f55,0x3f7f3f7b,0x3dc93e48,0xbf7bbf80,0x3e480000,0x3e480000,0x3f7b3f80,
0xbf55bf6d,0x3f0e3ec4,0x3f0e3ec4,0x3f553f6d,0xbf0ebf35,0x3f553f35,0x3f553f35,0x3f0e3f35,0xbe48bec4,0x3f7b3f6d,0x3f7b3f6d,0x3e483ec4,
0xbe950000,0xbf75bf80,0xbef1bf35,0x3f623f35,0xbf46bf0e,0xbf22bf55,0x3dc9be48,0x3f7f3f7b,0xbf7fbf6d,0xbdc9bec4,0x3f223ec4,0x3f463f6d,
0xbf62bf7b,0x3ef13e48,0x3f753f55,0x3e953f0e,0x3f6d3f80,0xbec40000,0xbf6dbf80,0x3ec40000,0x3ec43f35,0xbf6dbf35,0xbec4bf35,0x3f6d3f35,
0xbec40000,0xbf6dbf80,0x3ec40000,0x3f6d3f80,0xbf6dbf35,0xbec4bf35,0x3f6d3f35,0x3ec43f35,0x3ef10000,0x3f623f80,0xbf75bf35,0xbe95bf35,
0x3f7f3f55,0x3dc93f0e,0xbf46bf7b,0x3f223e48,0x3f223f6d,0xbf46bec4,0x3dc9bec4,0x3f7f3f6d,0xbe953e48,0xbf75bf7b,0x3f623f0e,0x3ef13f55,
0xbf55bf80,0x3f0e0000,0xbf0e0000,0xbf55bf80,0x3e48bec4,0x3f7b3f6d,0xbf7bbf6d,0x3e48bec4,0x3f7b3f35,0x3e483f35,0xbe48bf35,0x3f7b3f35,
0x3f0e3f6d,0xbf55bec4,0x3f553ec4,0x3f0e3f6d,0xbf220000,0xbf46bf80,0x3dc93f35,0xbf7fbf35,0xbf62bf7b,0x3ef1be48,0xbf75bf0e,0xbe95bf55,
0x3e95bec4,0x3f753f6d,0xbef1bf6d,0x3f623ec4,0x3f7f3f55,0xbdc93f0e,0x3f463e48,0x3f223f7b,0x3f353f80,0xbf350000,0x3f353f80,0xbf350000,
0xbf350000,0xbf35bf80,0xbf350000,0xbf35bf80,0xbf35bf80,0x3f350000,0xbf35bf80,0x3f350000,0x3f350000,0x3f353f80,0x3f350000,0x3f353f80,
0x3f460000,0x3f223f80,0x3f7f3f35,0xbdc93f35,0x3ef13f7b,0xbf62be48,0xbe953f0e,0xbf75bf55,0xbf75bec4,0xbe95bf6d,0xbf62bf6d,0x3ef1bec4,
0xbdc9bf55,0x3f7f3f0e,0x3f22be48,0x3f463f7b,0xbf0ebf80,0x3f550000,0x3f550000,0x3f0e3f80,0x3f7b3ec4,0x3e483f6d,0x3e483f6d,0xbf7bbec4,
0xbe483f35,0xbf7bbf35,0xbf7bbf35,0x3e48bf35,0xbf55bf6d,0x3f0ebec4,0x3f0ebec4,0x3f553f6d,0xbf620000,0xbef1bf80,0x3e95bf35,0x3f753f35,
0x3dc9bf55,0x3f7f3f0e,0x3f223f7b,0xbf463e48,0x3f463f6d,0xbf223ec4,0xbf7fbec4,0xbdc9bf6d,0xbf75be48,0xbe95bf7b,0x3ef1bf0e,0x3f623f55,
0x3ec43f80,0xbf6d0000,0xbec4bf80,0x3f6d0000,0xbf6dbf35,0x3ec4bf35,0x3f6d3f35,0xbec43f35,0x3f6d0000,0x3ec43f80,0xbf6d0000,0xbec4bf80,
0xbec43f35,0xbf6dbf35,0x3ec4bf35,0x3f6d3f35,0x3f750000,0x3e953f80,0xbf62bf35,0x3ef1bf35,0xbf223f0e,0xbf46bf55,0x3f7f3e48,0x3dc93f7b,
0x3dc9bf6d,0x3f7f3ec4,0xbf463ec4,0xbf22bf6d,0x3ef13f7b,0xbf623e48,0x3e95bf55,0x3f753f0e,0xbe48bf80,0x3f7b0000,0xbf7b0000,0xbe48bf80,
0x3f0e3f6d,0xbf553ec4,0x3f55bec4,0x3f0e3f6d,0xbf55bf35,0x3f0ebf35,0xbf0e3f35,0xbf55bf35,0x3f7b3ec4,0xbe483f6d,0x3e48bf6d,0x3f7b3ec4,
0xbf7f0000,0xbdc9bf80,0xbf223f35,0xbf46bf35,0x3f75be48,0x3e953f7b,0x3ef1bf55,0x3f623f0e,0xbf623ec4,0xbef1bf6d,0xbe953f6d,0xbf75bec4,
0x3f46bf0e,0x3f223f55,0x3dc9bf7b,0x3f7f3e48,0x3f80,0xbf800000,0x3f80,0xbf800000,0xbf80,0x3f800000,0xbf80,0x3f800000,
0x3f80,0xbf800000,0x3f80,0xbf800000,0xbf80,0x3f800000,0xbf80,0x3f800000,0x3f7f0000,0xbdc93f80,0x3f223f35,0xbf463f35,
0xbf75be48,0x3e95bf7b,0xbef1bf55,0x3f62bf0e,0x3f623ec4,0xbef13f6d,0x3e953f6d,0xbf753ec4,0xbf46bf0e,0x3f22bf55,0xbdc9bf7b,0x3f7fbe48,
0x3e48bf80,0x3f7b0000,0x3f7b0000,0xbe483f80,0xbf0e3f6d,0xbf55bec4,0xbf55bec4,0x3f0ebf6d,0x3f55bf35,0x3f0e3f35,0x3f0e3f35,0xbf553f35,
0xbf7b3ec4,0xbe48bf6d,0xbe48bf6d,0x3f7bbec4,0xbf750000,0x3e95bf80,0x3f62bf35,0x3ef13f35,0x3f223f0e,0xbf463f55,0xbf7f3e48,0x3dc9bf7b,
0xbdc9bf6d,0x3f7fbec4,0x3f463ec4,0xbf223f6d,0xbef13f7b,0xbf62be48,0xbe95bf55,0x3f75bf0e,0xbec43f80,0xbf6d0000,0x3ec4bf80,0x3f6d0000,
0x3f6dbf35,0x3ec43f35,0xbf6d3f35,0xbec4bf35,0xbf6d0000,0x3ec4bf80,0x3f6d0000,0xbec43f80,0x3ec43f35,0xbf6d3f35,0xbec4bf35,0x3f6dbf35,
0x3f620000,0xbef13f80,0xbe95bf35,0x3f75bf35,0xbdc9bf55,0x3f7fbf0e,0xbf223f7b,0xbf46be48,0xbf463f6d,0xbf22bec4,0x3f7fbec4,0xbdc93f6d,
0x3f75be48,0xbe953f7b,0xbef1bf0e,0x3f62bf55,0x3f0ebf80,0x3f550000,0xbf550000,0x3f0ebf80,0xbf7b3ec4,0x3e48bf6d,0xbe483f6d,0xbf7b3ec4,
0x3e483f35,0xbf7b3f35,0x3f7bbf35,0x3e483f35,0x3f55bf6d,0x3f0e3ec4,0xbf0ebec4,0x3f55bf6d,0xbf460000,0x3f22bf80,0xbf7f3f35,0xbdc9bf35,
0xbef13f7b,0xbf623e48,0x3e953f0e,0xbf753f55,0x3f75bec4,0xbe953f6d,0x3f62bf6d,0x3ef13ec4,0x3dc9bf55,0x3f7fbf0e,0xbf22be48,0x3f46bf7b,
0xbf353f80,0xbf350000,0xbf353f80,0xbf350000,0x3f350000,0xbf353f80,0x3f350000,0xbf353f80,0x3f35bf80,0x3f350000,0x3f35bf80,0x3f350000,
0xbf350000,0x3f35bf80,0xbf350000,0x3f35bf80,0x3f220000,0xbf463f80,0xbdc93f35,0xbf7f3f35,0x3f62bf7b,0x3ef13e48,0x3f75bf0e,0xbe953f55,
0xbe95bec4,0x3f75bf6d,0x3ef1bf6d,0x3f62bec4,0xbf7f3f55,0xbdc9bf0e,0xbf463e48,0x3f22bf7b,0x3f55bf80,0x3f0e0000,0x3f0e0000,0xbf553f80,
0xbe48bec4,0x3f7bbf6d,0x3f7bbf6d,0x3e483ec4,0xbf7b3f35,0x3e48bf35,0x3e48bf35,0x3f7bbf35,0xbf0e3f6d,0xbf553ec4,0xbf553ec4,0x3f0ebf6d,
0xbef10000,0x3f62bf80,0x3f75bf35,0xbe953f35,0xbf7f3f55,0x3dc9bf0e,0x3f46bf7b,0x3f22be48,0xbf223f6d,0xbf463ec4,0xbdc9bec4,0x3f7fbf6d,
0x3e953e48,0xbf753f7b,0xbf623f0e,0x3ef1bf55,0xbf6d3f80,0xbec40000,0x3f6dbf80,0x3ec40000,0xbec43f35,0xbf6d3f35,0x3ec4bf35,0x3f6dbf35,
0x3ec40000,0xbf6d3f80,0xbec40000,0x3f6dbf80,0x3f6dbf35,0xbec43f35,0xbf6d3f35,0x3ec4bf35,0x3e950000,0xbf753f80,0x3ef1bf35,0x3f62bf35,
0x3f46bf0e,0xbf223f55,0xbdc9be48,0x3f7fbf7b,0x3f7fbf6d,0xbdc93ec4,0xbf223ec4,0x3f46bf6d,0x3f62bf7b,0x3ef1be48,0xbf753f55,0x3e95bf0e,
0x3f7bbf80,0x3e480000,0xbe480000,0x3f7bbf80,0x3f55bf6d,0x3f0ebec4,0xbf0e3ec4,0x3f55bf6d,0x3f0ebf35,0x3f55bf35,0xbf553f35,0x3f0ebf35,
0x3e48bec4,0x3f7bbf6d,0xbf7b3f6d,0x3e48bec4,0xbdc90000,0x3f7fbf80,0xbf463f35,0x3f22bf35,0xbe953e48,0x3f75bf7b,0xbf623f55,0x3ef1bf0e,
0xbef13ec4,0x3f62bf6d,0xbf753f6d,0x3e95bec4,0xbf223f0e,0x3f46bf55,0xbf7f3f7b,0x3dc9be48,0x40003f80,0x3fb53f80,0x3f80,0xbfb53f80,
0x40004000,0xbfb50000,0x0,0xbfb5c000,0x40004000,0xbfb5c000,0x0,0x3fb50000,0x40004000,0x3fb50000,0x0,0x3fb54000,
0x3fff3f80,0x3fa23f80,0xbe49bf80,0xbfc6bf80,0x3ff53ffb,0xbfe2bec8,0xbf15bec8,0xbf71bffb,0x3fe23fed,0xbf15bfed,0xbf71bf44,0x3ff53f44,
0x3fc63fd5,0x3fff3f8e,0xbfa2bf8e,0x3e493fd5,0x3ffb3f80,0x3f8e3f80,0xbec83f80,0xbfd53f80,0x3fd53fed,0xbffbbf44,0xbf8ebf44,0xbec8bfed,
0x3f8e3fb5,0x3ec8bfb5,0xbfd5bfb5,0x3ffb3fb5,0x3ec83f44,0x3fd53fed,0xbffbbfed,0xbf8e3f44,0x3ff53f80,0x3f713f80,0xbf15bf80,0xbfe2bf80,
0x3fa23fd5,0xbfffbf8e,0xbfc6bf8e,0x3e49bfd5,0x3e493f44,0x3fa2bf44,0xbfffbfed,0x3fc63fed,0xbf71bec8,0x3f153ffb,0xbfe2bffb,0xbff5bec8,
0x3fed3f80,0x3f443f80,0xbf443f80,0xbfed3f80,0x3f443fb5,0xbfedbfb5,0xbfedbfb5,0x3f44bfb5,0xbf440000,0x3fed0000,0xbfedc000,0x3f444000,
0xbfedbfb5,0xbf443fb5,0xbf44bfb5,0xbfedbfb5,0x3fe23f80,0x3f153f80,0xbf71bf80,0xbff5bf80,0x3e493f8e,0xbfc6bfd5,0xbfffbfd5,0x3fa2bf8e,
0xbfc6bf44,0x3fff3f44,0xbfa2bfed,0xbe493fed,0xbff5bffb,0xbfe23ec8,0x3f15bec8,0xbf71bffb,0x3fd53f80,0x3ec83f80,0xbf8e3f80,0xbffb3f80,
0xbec83f44,0xbf8ebfed,0xbffbbfed,0x3fd5bf44,0xbffbbfb5,0x3fd53fb5,0xbec8bfb5,0xbf8e3fb5,0xbf8ebfed,0xbffbbf44,0x3fd53f44,0x3ec8bfed,
0x3fc63f80,0x3e493f80,0xbfa2bf80,0xbfffbf80,0xbf713ec8,0xbf15bffb,0xbfe2bffb,0x3ff5bec8,0xbff5bfed,0x3f713fed,0x3f15bf44,0xbfe23f44,
0x3e49bf8e,0xbfa2bfd5,0x3fff3fd5,0x3fc6bf8e,0x3f80,0xbfb53f80,0xc0003f80,0xbfb53f80,0xc000,0x3fb50000,0x40000000,0xbfb54000,
0x4000,0x3fb5c000,0xc0000000,0x3fb50000,0xc000,0xbfb50000,0x40000000,0x3fb5c000,0xbe493f80,0xbfc63f80,0xbfffbf80,0xbfa2bf80,
0x3f15bffb,0x3f713ec8,0x3ff53ec8,0xbfe23ffb,0xbf713fed,0x3ff5bfed,0xbfe2bf44,0x3f153f44,0x3fa2bfd5,0xbe49bf8e,0x3fc63f8e,0x3fffbfd5,
0xbec83f80,0xbfd53f80,0xbffb3f80,0xbf8e3f80,0x3f8ebfed,0x3ec83f44,0x3fd53f44,0xbffb3fed,0xbfd53fb5,0x3ffbbfb5,0xbf8ebfb5,0xbec83fb5,
0x3ffbbf44,0x3f8ebfed,0x3ec83fed,0x3fd5bf44,0xbf153f80,0xbfe23f80,0xbff5bf80,0xbf71bf80,0x3fc6bfd5,0xbe493f8e,0x3fa23f8e,0xbfff3fd5,
0xbfff3f44,0x3fc6bf44,0xbe49bfed,0xbfa23fed,0x3fe23ec8,0x3ff5bffb,0xbf713ffb,0x3f153ec8,0xbf443f80,0xbfed3f80,0xbfed3f80,0xbf443f80,
0x3fedbfb5,0xbf443fb5,0x3f443fb5,0xbfed3fb5,0xbfed0000,0x3f440000,0x3f44c000,0xbfed4000,0x3f443fb5,0x3fedbfb5,0xbfed3fb5,0xbf443fb5,
0xbf713f80,0xbff53f80,0xbfe2bf80,0xbf15bf80,0x3fffbf8e,0xbfa23fd5,0x3e493fd5,0xbfc63f8e,0xbfa2bf44,0xbe493f44,0x3fc6bfed,0xbfff3fed,
0xbf153ffb,0x3f71bec8,0xbff53ec8,0xbfe23ffb,0xbf8e3f80,0xbffb3f80,0xbfd53f80,0xbec83f80,0x3ffbbf44,0xbfd53fed,0xbec83fed,0xbf8e3f44,
0xbec8bfb5,0xbf8e3fb5,0x3ffbbfb5,0xbfd53fb5,0xbfd53fed,0xbec83f44,0xbf8ebf44,0xbffb3fed,0xbfa23f80,0xbfff3f80,0xbfc6bf80,0xbe49bf80,
0x3fe2bec8,0xbff53ffb,0xbf713ffb,0xbf153ec8,0x3f15bfed,0xbfe23fed,0x3ff5bf44,0xbf713f44,0xbfff3f8e,0xbfc63fd5,0x3e49bfd5,0xbfa23f8e,
0xc0003f80,0xbfb53f80,0x3f80,0x3fb53f80,0xc0004000,0x3fb50000,0x0,0x3fb5c000,0xc0004000,0x3fb5c000,0x0,0xbfb50000,
0xc0004000,0xbfb50000,0x0,0xbfb54000,0xbfff3f80,0xbfa23f80,0x3e49bf80,0x3fc6bf80,0xbff53ffb,0x3fe2bec8,0x3f15bec8,0x3f71bffb,
0xbfe23fed,0x3f15bfed,0x3f71bf44,0xbff53f44,0xbfc63fd5,0xbfff3f8e,0x3fa2bf8e,0xbe493fd5,0xbffb3f80,0xbf8e3f80,0x3ec83f80,0x3fd53f80,
0xbfd53fed,0x3ffbbf44,0x3f8ebf44,0x3ec8bfed,0xbf8e3fb5,0xbec8bfb5,0x3fd5bfb5,0xbffb3fb5,0xbec83f44,0xbfd53fed,0x3ffbbfed,0x3f8e3f44,
0xbff53f80,0xbf713f80,0x3f15bf80,0x3fe2bf80,0xbfa23fd5,0x3fffbf8e,0x3fc6bf8e,0xbe49bfd5,0xbe493f44,0xbfa2bf44,0x3fffbfed,0xbfc63fed,
0x3f71bec8,0xbf153ffb,0x3fe2bffb,0x3ff5bec8,0xbfed3f80,0xbf443f80,0x3f443f80,0x3fed3f80,0xbf443fb5,0x3fedbfb5,0x3fedbfb5,0xbf44bfb5,
0x3f440000,0xbfed0000,0x3fedc000,0xbf444000,0x3fedbfb5,0x3f443fb5,0x3f44bfb5,0x3fedbfb5,0xbfe23f80,0xbf153f80,0x3f71bf80,0x3ff5bf80,
0xbe493f8e,0x3fc6bfd5,0x3fffbfd5,0xbfa2bf8e,0x3fc6bf44,0xbfff3f44,0x3fa2bfed,0x3e493fed,0x3ff5bffb,0x3fe23ec8,0xbf15bec8,0x3f71bffb,
0xbfd53f80,0xbec83f80,0x3f8e3f80,0x3ffb3f80,0x3ec83f44,0x3f8ebfed,0x3ffbbfed,0xbfd5bf44,0x3ffbbfb5,0xbfd53fb5,0x3ec8bfb5,0x3f8e3fb5,
0x3f8ebfed,0x3ffbbf44,0xbfd53f44,0xbec8bfed,0xbfc63f80,0xbe493f80,0x3fa2bf80,0x3fffbf80,0x3f713ec8,0x3f15bffb,0x3fe2bffb,0xbff5bec8,
0x3ff5bfed,0xbf713fed,0xbf15bf44,0x3fe23f44,0xbe49bf8e,0x3fa2bfd5,0xbfff3fd5,0xbfc6bf8e,0x3f80,0x3fb53f80,0x40003f80,0x3fb53f80,
0xc000,0xbfb50000,0xc0000000,0x3fb54000,0x4000,0xbfb5c000,0x40000000,0xbfb50000,0xc000,0x3fb50000,0xc0000000,0xbfb5c000,
0x3e493f80,0x3fc63f80,0x3fffbf80,0x3fa2bf80,0xbf15bffb,0xbf713ec8,0xbff53ec8,0x3fe23ffb,0x3f713fed,0xbff5bfed,0x3fe2bf44,0xbf153f44,
0xbfa2bfd5,0x3e49bf8e,0xbfc63f8e,0xbfffbfd5,0x3ec83f80,0x3fd53f80,0x3ffb3f80,0x3f8e3f80,0xbf8ebfed,0xbec83f44,0xbfd53f44,0x3ffb3fed,
0x3fd53fb5,0xbffbbfb5,0x3f8ebfb5,0x3ec83fb5,0xbffbbf44,0xbf8ebfed,0xbec83fed,0xbfd5bf44,0x3f153f80,0x3fe23f80,0x3ff5bf80,0x3f71bf80,
0xbfc6bfd5,0x3e493f8e,0xbfa23f8e,0x3fff3fd5,0x3fff3f44,0xbfc6bf44,0x3e49bfed,0x3fa23fed,0xbfe23ec8,0xbff5bffb,0x3f713ffb,0xbf153ec8,
0x3f443f80,0x3fed3f80,0x3fed3f80,0x3f443f80,0xbfedbfb5,0x3f443fb5,0xbf443fb5,0x3fed3fb5,0x3fed0000,0xbf440000,0xbf44c000,0x3fed4000,
0xbf443fb5,0xbfedbfb5,0x3fed3fb5,0x3f443fb5,0x3f713f80,0x3ff53f80,0x3fe2bf80,0x3f15bf80,0xbfffbf8e,0x3fa23fd5,0xbe493fd5,0x3fc63f8e,
0x3fa2bf44,0x3e493f44,0xbfc6bfed,0x3fff3fed,0x3f153ffb,0xbf71bec8,0x3ff53ec8,0x3fe23ffb,0x3f8e3f80,0x3ffb3f80,0x3fd53f80,0x3ec83f80,
0xbffbbf44,0x3fd53fed,0x3ec83fed,0x3f8e3f44,0x3ec8bfb5,0x3f8e3fb5,0xbffbbfb5,0x3fd53fb5,0x3fd53fed,0x3ec83f44,0x3f8ebf44,0x3ffb3fed,
0x3fa23f80,0x3fff3f80,0x3fc6bf80,0x3e49bf80,0xbfe2bec8,0x3ff53ffb,0x3f713ffb,0x3f153ec8,0xbf15bfed,0x3fe23fed,0xbff5bf44,0x3f713f44,
0x3fff3f8e,0x3fc63fd5,0xbe49bfd5,0x3fa23f8e,0x40004000,0x3fb54000,0x0,0xbfb50000,0x40004000,0xbfb50000,0x0,0xbfb5c000,
0x40004000,0xbfb5c000,0x0,0x3fb50000,0x40004000,0x3fb50000,0x0,0x3fb54000,0x3fa23fb5,0xbe493fb5,0xbfc6bfb5,0xbfffbfb5,
0x3f713f8e,0xbff5bfd5,0xbfe2bfd5,0x3f15bf8e,0x3f153f44,0x3f71bf44,0xbff5bfed,0x3fe23fed,0x3e493ec8,0x3fc63ffb,0xbfffbffb,0xbfa23ec8,
0xbec80000,0xbfd50000,0xbffbc000,0xbf8ec000,0xbf8ebf44,0xbec8bfed,0xbfd5bfed,0x3ffb3f44,0xbfd5bfb5,0x3ffb3fb5,0xbf8ebfb5,0xbec83fb5,
0xbffbbfed,0xbf8e3f44,0xbec8bf44,0xbfd5bfed,0xbfe2bfb5,0xbff5bfb5,0xbf71bfb5,0x3f15bfb5,0xbfffbffb,0x3fc6bec8,0x3e49bec8,0x3fa23ffb,
0xbfc6bfed,0x3e493fed,0x3fa23f44,0xbfffbf44,0xbf15bf8e,0xbfe2bfd5,0x3ff53fd5,0x3f71bf8e,0xbfedc000,0xbf44c000,0x3f440000,0x3fed0000,
0xbf44bfb5,0x3fed3fb5,0x3fed3fb5,0xbf443fb5,0x3f440000,0xbfed0000,0x3fed4000,0xbf44c000,0x3fed3fb5,0x3f44bfb5,0x3f443fb5,0x3fed3fb5,
0xbf15bfb5,0x3f71bfb5,0x3ff53fb5,0x3fe23fb5,0x3fa23ec8,0x3e493ffb,0x3fc63ffb,0xbfffbec8,0x3fff3fed,0xbfa2bfed,0xbe493f44,0x3fc6bf44,
0x3f713fd5,0x3ff53f8e,0xbfe2bf8e,0xbf153fd5,0x3f8e0000,0x3ffb0000,0x3fd54000,0x3ec84000,0x3ffb3fed,0xbfd53f44,0xbec83f44,0xbf8ebfed,
0x3ec83fb5,0x3f8ebfb5,0xbffbbfb5,0x3fd53fb5,0xbfd5bf44,0xbec83fed,0xbf8ebfed,0xbffbbf44,0x3fff3fb5,0x3fc63fb5,0x3e493fb5,0xbfa23fb5,
0x3f153fd5,0xbfe2bf8e,0xbff5bf8e,0x3f71bfd5,0xbfe2bf44,0x3ff53f44,0xbf71bfed,0xbf153fed,0xbfa2bffb,0xbfffbec8,0x3fc63ec8,0x3e49bffb,
0x4000,0xbfb54000,0xc0000000,0xbfb50000,0xc000,0x3fb50000,0x40000000,0xbfb54000,0x4000,0x3fb5c000,0xc0000000,0x3fb50000,
0xc000,0xbfb50000,0x40000000,0x3fb5c000,0xbfc63fb5,0xbfff3fb5,0xbfa2bfb5,0x3e49bfb5,0x3fe2bf8e,0xbf153fd5,0x3f713fd5,0xbff53f8e,
0xbff53f44,0x3fe2bf44,0xbf15bfed,0xbf713fed,0x3fffbec8,0x3fa2bffb,0x3e493ffb,0x3fc6bec8,0xbffb0000,0xbf8e0000,0x3ec8c000,0x3fd5c000,
0x3fd53f44,0xbffb3fed,0xbf8e3fed,0xbec8bf44,0xbf8ebfb5,0xbec83fb5,0x3fd5bfb5,0xbffb3fb5,0x3ec83fed,0x3fd5bf44,0xbffb3f44,0xbf8e3fed,
0xbf71bfb5,0x3f15bfb5,0x3fe2bfb5,0x3ff5bfb5,0xbe493ffb,0xbfa23ec8,0xbfff3ec8,0x3fc6bffb,0x3fa2bfed,0xbfff3fed,0x3fc63f44,0xbe49bf44,
0xbff53f8e,0xbf713fd5,0xbf15bfd5,0xbfe23f8e,0x3f44c000,0x3fedc000,0x3fed0000,0x3f440000,0xbfed3fb5,0x3f44bfb5,0xbf44bfb5,0x3fedbfb5,
0x3fed0000,0xbf440000,0xbf444000,0x3fedc000,0xbf44bfb5,0xbfed3fb5,0x3fedbfb5,0x3f44bfb5,0x3ff5bfb5,0x3fe2bfb5,0x3f153fb5,0xbf713fb5,
0xbfc6bec8,0x3fffbffb,0x3fa2bffb,0x3e493ec8,0xbe493fed,0x3fc6bfed,0xbfff3f44,0x3fa2bf44,0x3fe2bfd5,0x3f15bf8e,0x3f713f8e,0x3ff5bfd5,
0x3fd50000,0x3ec80000,0xbf8e4000,0xbffb4000,0x3ec8bfed,0x3f8ebf44,0x3ffbbf44,0xbfd53fed,0xbffb3fb5,0x3fd5bfb5,0xbec8bfb5,0xbf8e3fb5,
0x3f8e3f44,0x3ffbbfed,0xbfd53fed,0xbec83f44,0x3e493fb5,0xbfa23fb5,0xbfff3fb5,0xbfc63fb5,0x3ff5bfd5,0xbf713f8e,0x3f153f8e,0xbfe23fd5,
0xbf71bf44,0xbf153f44,0x3fe2bfed,0xbff53fed,0xbfc63ffb,0xbe493ec8,0xbfa2bec8,0xbfff3ffb,0xc0004000,0xbfb54000,0x0,0x3fb50000,
0xc0004000,0x3fb50000,0x0,0x3fb5c000,0xc0004000,0x3fb5c000,0x0,0xbfb50000,0xc0004000,0xbfb50000,0x0,0xbfb54000,
0xbfa23fb5,0x3e493fb5,0x3fc6bfb5,0x3fffbfb5,0xbf713f8e,0x3ff5bfd5,0x3fe2bfd5,0xbf15bf8e,0xbf153f44,0xbf71bf44,0x3ff5bfed,0xbfe23fed,
0xbe493ec8,0xbfc63ffb,0x3fffbffb,0x3fa23ec8,0x3ec80000,0x3fd50000,0x3ffbc000,0x3f8ec000,0x3f8ebf44,0x3ec8bfed,0x3fd5bfed,0xbffb3f44,
0x3fd5bfb5,0xbffb3fb5,0x3f8ebfb5,0x3ec83fb5,0x3ffbbfed,0x3f8e3f44,0x3ec8bf44,0x3fd5bfed,0x3fe2bfb5,0x3ff5bfb5,0x3f71bfb5,0xbf15bfb5,
0x3fffbffb,0xbfc6bec8,0xbe49bec8,0xbfa23ffb,0x3fc6bfed,0xbe493fed,0xbfa23f44,0x3fffbf44,0x3f15bf8e,0x3fe2bfd5,0xbff53fd5,0xbf71bf8e,
0x3fedc000,0x3f44c000,0xbf440000,0xbfed0000,0x3f44bfb5,0xbfed3fb5,0xbfed3fb5,0x3f443fb5,0xbf440000,0x3fed0000,0xbfed4000,0x3f44c000,
0xbfed3fb5,0xbf44bfb5,0xbf443fb5,0xbfed3fb5,0x3f15bfb5,0xbf71bfb5,0xbff53fb5,0xbfe23fb5,0xbfa23ec8,0xbe493ffb,0xbfc63ffb,0x3fffbec8,
0xbfff3fed,0x3fa2bfed,0x3e493f44,0xbfc6bf44,0xbf713fd5,0xbff53f8e,0x3fe2bf8e,0x3f153fd5,0xbf8e0000,0xbffb0000,0xbfd54000,0xbec84000,
0xbffb3fed,0x3fd53f44,0x3ec83f44,0x3f8ebfed,0xbec83fb5,0xbf8ebfb5,0x3ffbbfb5,0xbfd53fb5,0x3fd5bf44,0x3ec83fed,0x3f8ebfed,0x3ffbbf44,
0xbfff3fb5,0xbfc63fb5,0xbe493fb5,0x3fa23fb5,0xbf153fd5,0x3fe2bf8e,0x3ff5bf8e,0xbf71bfd5,0x3fe2bf44,0xbff53f44,0x3f71bfed,0x3f153fed,
0x3fa2bffb,0x3fffbec8,0xbfc63ec8,0xbe49bffb,0x4000,0x3fb54000,0x40000000,0x3fb50000,0xc000,0xbfb50000,0xc0000000,0x3fb54000,
0x4000,0xbfb5c000,0x40000000,0xbfb50000,0xc000,0x3fb50000,0xc0000000,0xbfb5c000,0x3fc63fb5,0x3fff3fb5,0x3fa2bfb5,0xbe49bfb5,
0xbfe2bf8e,0x3f153fd5,0xbf713fd5,0x3ff53f8e,0x3ff53f44,0xbfe2bf44,0x3f15bfed,0x3f713fed,0xbfffbec8,0xbfa2bffb,0xbe493ffb,0xbfc6bec8,
0x3ffb0000,0x3f8e0000,0xbec8c000,0xbfd5c000,0xbfd53f44,0x3ffb3fed,0x3f8e3fed,0x3ec8bf44,0x3f8ebfb5,0x3ec83fb5,0xbfd5bfb5,0x3ffb3fb5,
0xbec83fed,0xbfd5bf44,0x3ffb3f44,0x3f8e3fed,0x3f71bfb5,0xbf15bfb5,0xbfe2bfb5,0xbff5bfb5,0x3e493ffb,0x3fa23ec8,0x3fff3ec8,0xbfc6bffb,
0xbfa2bfed,0x3fff3fed,0xbfc63f44,0x3e49bf44,0x3ff53f8e,0x3f713fd5,0x3f15bfd5,0x3fe23f8e,0xbf44c000,0xbfedc000,0xbfed0000,0xbf440000,
0x3fed3fb5,0xbf44bfb5,0x3f44bfb5,0xbfedbfb5,0xbfed0000,0x3f440000,0x3f444000,0xbfedc000,0x3f44bfb5,0x3fed3fb5,0xbfedbfb5,0xbf44bfb5,
0xbff5bfb5,0xbfe2bfb5,0xbf153fb5,0x3f713fb5,0x3fc6bec8,0xbfffbffb,0xbfa2bffb,0xbe493ec8,0x3e493fed,0xbfc6bfed,0x3fff3f44,0xbfa2bf44,
0xbfe2bfd5,0xbf15bf8e,0xbf713f8e,0xbff5bfd5,0xbfd50000,0xbec80000,0x3f8e4000,0x3ffb4000,0xbec8bfed,0xbf8ebf44,0xbffbbf44,0x3fd53fed,
0x3ffb3fb5,0xbfd5bfb5,0x3ec8bfb5,0x3f8e3fb5,0xbf8e3f44,0xbffbbfed,0x3fd53fed,0x3ec83f44,0xbe493fb5,0x3fa23fb5,0x3fff3fb5,0x3fc63fb5,
0xbff5bfd5,0x3f713f8e,0xbf153f8e,0x3fe23fd5,0x3f71bf44,0x3f153f44,0xbfe2bfed,0x3ff53fed,0x3fc63ffb,0x3e493ec8,0x3fa2bec8,0x3fff3ffb,
0x40004000,0x3fb54000,0x0,0xbfb50000,0x40004000,0xbfb50000,0x0,0xbfb5c000,0x40004000,0xbfb5c000,0x0,0x3fb50000,
0x40004000,0x3fb50000,0x0,0x3fb54000,0xbe490000,0xbfc60000,0xbfffc000,0xbfa2c000,0xbf15bec8,0xbf71bffb,0xbff5bffb,0x3fe23ec8,
0xbf71bf44,0x3ff53f44,0xbfe2bfed,0x3f153fed,0xbfa2bf8e,0x3e493fd5,0xbfc6bfd5,0xbfffbf8e,0xbffbc000,0xbf8ec000,0x3ec80000,0x3fd50000,
0xbfd5bfed,0x3ffb3f44,0x3f8e3f44,0x3ec83fed,0xbf8ebfb5,0xbec83fb5,0x3fd53fb5,0xbffbbfb5,0xbec8bf44,0xbfd5bfed,0x3ffb3fed,0x3f8ebf44,
0x3f150000,0x3fe20000,0x3ff54000,0x3f714000,0x3fc63f8e,0xbe493fd5,0x3fa23fd5,0xbfffbf8e,0x3fff3fed,0xbfc6bfed,0x3e493f44,0x3fa2bf44,
0x3fe23ffb,0x3ff53ec8,0xbf71bec8,0x3f153ffb,0x3fed4000,0x3f444000,0xbf440000,0xbfed0000,0x3f443fb5,0xbfedbfb5,0xbfedbfb5,0x3f44bfb5,
0xbf440000,0x3fed0000,0xbfedc000,0x3f444000,0xbfedbfb5,0xbf443fb5,0xbf44bfb5,0xbfedbfb5,0xbf710000,0xbff50000,0xbfe2c000,0xbf15c000,
0xbfffbfd5,0x3fa2bf8e,0xbe49bf8e,0x3fc63fd5,0xbfa2bfed,0xbe493fed,0x3fc63f44,0xbfffbf44,0x3f15bec8,0xbf71bffb,0x3ff53ffb,0x3fe2bec8,
0xbfd5c000,0xbec8c000,0x3f8e0000,0x3ffb0000,0x3ec8bf44,0x3f8e3fed,0x3ffb3fed,0xbfd53f44,0x3ffb3fb5,0xbfd5bfb5,0x3ec83fb5,0x3f8ebfb5,
0x3f8e3fed,0x3ffb3f44,0xbfd5bf44,0xbec83fed,0x3fa20000,0x3fff0000,0x3fc64000,0x3e494000,0x3fe23ffb,0xbff53ec8,0xbf713ec8,0xbf15bffb,
0xbf153f44,0x3fe2bf44,0xbff5bfed,0x3f713fed,0xbfffbfd5,0xbfc63f8e,0x3e49bf8e,0xbfa2bfd5,0x4000,0xbfb54000,0xc0000000,0xbfb50000,
0xc000,0x3fb50000,0x40000000,0xbfb54000,0x4000,0x3fb5c000,0xc0000000,0x3fb50000,0xc000,0xbfb50000,0x40000000,0x3fb5c000,
0xbfff0000,0xbfa20000,0x3e49c000,0x3fc6c000,0x3ff53ec8,0xbfe23ffb,0xbf153ffb,0xbf71bec8,0xbfe2bf44,0x3f153f44,0x3f71bfed,0xbff53fed,
0x3fc63f8e,0x3fffbfd5,0xbfa23fd5,0x3e493f8e,0x3ec8c000,0x3fd5c000,0x3ffb0000,0x3f8e0000,0xbf8e3fed,0xbec8bf44,0xbfd5bf44,0x3ffbbfed,
0x3fd5bfb5,0xbffb3fb5,0x3f8e3fb5,0x3ec8bfb5,0xbffb3f44,0xbf8e3fed,0xbec8bfed,0xbfd53f44,0x3ff50000,0x3f710000,0xbf154000,0xbfe24000,
0xbfa2bf8e,0x3fffbfd5,0x3fc6bfd5,0xbe493f8e,0x3e493fed,0x3fa2bfed,0xbfff3f44,0x3fc6bf44,0x3f71bffb,0xbf15bec8,0x3fe23ec8,0x3ff5bffb,
0xbf444000,0xbfed4000,0xbfed0000,0xbf440000,0x3fedbfb5,0xbf443fb5,0x3f443fb5,0xbfed3fb5,0xbfed0000,0x3f440000,0x3f44c000,0xbfed4000,
0x3f443fb5,0x3fedbfb5,0xbfed3fb5,0xbf443fb5,0xbfe20000,0xbf150000,0x3f71c000,0x3ff5c000,0x3e493fd5,0xbfc63f8e,0xbfff3f8e,0x3fa2bfd5,
0x3fc6bfed,0xbfff3fed,0x3fa23f44,0x3e49bf44,0xbff53ec8,0xbfe23ffb,0x3f15bffb,0xbf713ec8,0x3f8ec000,0x3ffbc000,0x3fd50000,0x3ec80000,
0xbffb3f44,0x3fd5bfed,0x3ec8bfed,0x3f8ebf44,0x3ec83fb5,0x3f8ebfb5,0xbffb3fb5,0x3fd5bfb5,0x3fd5bfed,0x3ec8bf44,0x3f8e3f44,0x3ffbbfed,
0x3fc60000,0x3e490000,0xbfa24000,0xbfff4000,0x3f71bffb,0x3f15bec8,0x3fe2bec8,0xbff53ffb,0xbff53f44,0x3f71bf44,0x3f15bfed,0xbfe23fed,
0xbe493fd5,0x3fa2bf8e,0xbfff3f8e,0xbfc63fd5,0xc0004000,0xbfb54000,0x0,0x3fb50000,0xc0004000,0x3fb50000,0x0,0x3fb5c000,
0xc0004000,0x3fb5c000,0x0,0xbfb50000,0xc0004000,0xbfb50000,0x0,0xbfb54000,0x3e490000,0x3fc60000,0x3fffc000,0x3fa2c000,
0x3f15bec8,0x3f71bffb,0x3ff5bffb,0xbfe23ec8,0x3f71bf44,0xbff53f44,0x3fe2bfed,0xbf153fed,0x3fa2bf8e,0xbe493fd5,0x3fc6bfd5,0x3fffbf8e,
0x3ffbc000,0x3f8ec000,0xbec80000,0xbfd50000,0x3fd5bfed,0xbffb3f44,0xbf8e3f44,0xbec83fed,0x3f8ebfb5,0x3ec83fb5,0xbfd53fb5,0x3ffbbfb5,
0x3ec8bf44,0x3fd5bfed,0xbffb3fed,0xbf8ebf44,0xbf150000,0xbfe20000,0xbff54000,0xbf714000,0xbfc63f8e,0x3e493fd5,0xbfa23fd5,0x3fffbf8e,
0xbfff3fed,0x3fc6bfed,0xbe493f44,0xbfa2bf44,0xbfe23ffb,0xbff53ec8,0x3f71bec8,0xbf153ffb,0xbfed4000,0xbf444000,0x3f440000,0x3fed0000,
0xbf443fb5,0x3fedbfb5,0x3fedbfb5,0xbf44bfb5,0x3f440000,0xbfed0000,0x3fedc000,0xbf444000,0x3fedbfb5,0x3f443fb5,0x3f44bfb5,0x3fedbfb5,
0x3f710000,0x3ff50000,0x3fe2c000,0x3f15c000,0x3fffbfd5,0xbfa2bf8e,0x3e49bf8e,0xbfc63fd5,0x3fa2bfed,0x3e493fed,0xbfc63f44,0x3fffbf44,
0xbf15bec8,0x3f71bffb,0xbff53ffb,0xbfe2bec8,0x3fd5c000,0x3ec8c000,0xbf8e0000,0xbffb0000,0xbec8bf44,0xbf8e3fed,0xbffb3fed,0x3fd53f44,
0xbffb3fb5,0x3fd5bfb5,0xbec83fb5,0xbf8ebfb5,0xbf8e3fed,0xbffb3f44,0x3fd5bf44,0x3ec83fed,0xbfa20000,0xbfff0000,0xbfc64000,0xbe494000,
0xbfe23ffb,0x3ff53ec8,0x3f713ec8,0x3f15bffb,0x3f153f44,0xbfe2bf44,0x3ff5bfed,0xbf713fed,0x3fffbfd5,0x3fc63f8e,0xbe49bf8e,0x3fa2bfd5,
0x4000,0x3fb54000,0x40000000,0x3fb50000,0xc000,0xbfb50000,0xc0000000,0x3fb54000,0x4000,0xbfb5c000,0x40000000,0xbfb50000,
0xc000,0x3fb50000,0xc0000000,0xbfb5c000,0x3fff0000,0x3fa20000,0xbe49c000,0xbfc6c000,0xbff53ec8,0x3fe23ffb,0x3f153ffb,0x3f71bec8,
0x3fe2bf44,0xbf153f44,0xbf71bfed,0x3ff53fed,0xbfc63f8e,0xbfffbfd5,0x3fa23fd5,0xbe493f8e,0xbec8c000,0xbfd5c000,0xbffb0000,0xbf8e0000,
0x3f8e3fed,0x3ec8bf44,0x3fd5bf44,0xbffbbfed,0xbfd5bfb5,0x3ffb3fb5,0xbf8e3fb5,0xbec8bfb5,0x3ffb3f44,0x3f8e3fed,0x3ec8bfed,0x3fd53f44,
0xbff50000,0xbf710000,0x3f154000,0x3fe24000,0x3fa2bf8e,0xbfffbfd5,0xbfc6bfd5,0x3e493f8e,0xbe493fed,0xbfa2bfed,0x3fff3f44,0xbfc6bf44,
0xbf71bffb,0x3f15bec8,0xbfe23ec8,0xbff5bffb,0x3f444000,0x3fed4000,0x3fed0000,0x3f440000,0xbfedbfb5,0x3f443fb5,0xbf443fb5,0x3fed3fb5,
0x3fed0000,0xbf440000,0xbf44c000,0x3fed4000,0xbf443fb5,0xbfedbfb5,0x3fed3fb5,0x3f443fb5,0x3fe20000,0x3f150000,0xbf71c000,0xbff5c000,
0xbe493fd5,0x3fc63f8e,0x3fff3f8e,0xbfa2bfd5,0xbfc6bfed,0x3fff3fed,0xbfa23f44,0xbe49bf44,0x3ff53ec8,0x3fe23ffb,0xbf15bffb,0x3f713ec8,
0xbf8ec000,0xbffbc000,0xbfd50000,0xbec80000,0x3ffb3f44,0xbfd5bfed,0xbec8bfed,0xbf8ebf44,0xbec83fb5,0xbf8ebfb5,0x3ffb3fb5,0xbfd5bfb5,
0xbfd5bfed,0xbec8bf44,0xbf8e3f44,0xbffbbfed,0xbfc60000,0xbe490000,0x3fa24000,0x3fff4000,0xbf71bffb,0xbf15bec8,0xbfe2bec8,0x3ff53ffb,
0x3ff53f44,0xbf71bf44,0xbf15bfed,0x3fe23fed,0x3e493fd5,0xbfa2bf8e,0x3fff3f8e,0x3fc63fd5,0x40004000,0x3fb54000,0x0,0xbfb50000,
0x40004000,0xbfb50000,0x0,0xbfb5c000,0x40004000,0xbfb5c000,0x0,0x3fb50000,0x40004000,0x3fb50000,0x0,0x3fb54000,
0xbfc6bfb5,0xbfffbfb5,0xbfa2bfb5,0x3e49bfb5,0xbfe2bfd5,0x3f15bf8e,0xbf71bf8e,0x3ff53fd5,0xbff5bfed,0x3fe23fed,0xbf15bf44,0xbf713f44,
0xbfffbffb,0xbfa23ec8,0xbe49bec8,0xbfc6bffb,0x3ec80000,0x3fd50000,0x3ffb4000,0x3f8e4000,0x3f8e3f44,0x3ec83fed,0x3fd53fed,0xbffbbf44,
0x3fd53fb5,0xbffbbfb5,0x3f8e3fb5,0x3ec8bfb5,0x3ffb3fed,0x3f8ebf44,0x3ec83f44,0x3fd53fed,0x3f713fb5,0xbf153fb5,0xbfe2bfb5,0xbff5bfb5,
0xbe493ec8,0xbfa2bffb,0xbfffbffb,0x3fc6bec8,0xbfa2bf44,0x3fff3f44,0xbfc6bfed,0x3e493fed,0xbff5bfd5,0xbf713f8e,0xbf15bf8e,0xbfe2bfd5,
0xbfedc000,0xbf44c000,0x3f440000,0x3fed0000,0xbf44bfb5,0x3fed3fb5,0x3fed3fb5,0xbf443fb5,0x3f440000,0xbfed0000,0x3fed4000,0xbf44c000,
0x3fed3fb5,0x3f44bfb5,0x3f443fb5,0x3fed3fb5,0x3ff53fb5,0x3fe23fb5,0x3f153fb5,0xbf713fb5,0x3fc63ffb,0xbfffbec8,0xbfa2bec8,0xbe49bffb,
0xbe493f44,0x3fc6bf44,0xbfffbfed,0x3fa23fed,0xbfe2bf8e,0xbf153fd5,0xbf71bfd5,0xbff5bf8e,0xbf8e0000,0xbffb0000,0xbfd5c000,0xbec8c000,
0xbffbbfed,0x3fd5bf44,0x3ec8bf44,0x3f8e3fed,0xbec8bfb5,0xbf8e3fb5,0x3ffb3fb5,0xbfd5bfb5,0x3fd53f44,0x3ec8bfed,0x3f8e3fed,0x3ffb3f44,
0xbe49bfb5,0x3fa2bfb5,0x3fff3fb5,0x3fc63fb5,0x3ff53f8e,0xbf713fd5,0x3f153fd5,0xbfe2bf8e,0x3f713fed,0x3f15bfed,0xbfe2bf44,0x3ff53f44,
0xbfc6bec8,0xbe493ffb,0xbfa2bffb,0xbfffbec8,0x4000,0xbfb54000,0xc0000000,0xbfb50000,0xc000,0x3fb50000,0x40000000,0xbfb54000,
0x4000,0x3fb5c000,0xc0000000,0x3fb50000,0xc000,0xbfb50000,0x40000000,0x3fb5c000,0xbfa2bfb5,0x3e49bfb5,0x3fc6bfb5,0x3fffbfb5,
0x3f713fd5,0xbff53f8e,0xbfe23f8e,0x3f15bfd5,0xbf15bfed,0xbf713fed,0x3ff5bf44,0xbfe23f44,0x3e493ffb,0x3fc6bec8,0xbfff3ec8,0xbfa23ffb,
0x3ffb0000,0x3f8e0000,0xbec84000,0xbfd54000,0xbfd5bf44,0x3ffbbfed,0x3f8ebfed,0x3ec83f44,0x3f8e3fb5,0x3ec8bfb5,0xbfd53fb5,0x3ffbbfb5,
0xbec8bfed,0xbfd53f44,0x3ffbbf44,0x3f8ebfed,0xbfe23fb5,0xbff53fb5,0xbf71bfb5,0x3f15bfb5,0x3fffbec8,0xbfc63ffb,0xbe493ffb,0xbfa23ec8,
0xbfc6bf44,0x3e493f44,0x3fa2bfed,0xbfff3fed,0x3f153fd5,0x3fe2bf8e,0xbff53f8e,0xbf713fd5,0x3f44c000,0x3fedc000,0x3fed0000,0x3f440000,
0xbfed3fb5,0x3f44bfb5,0xbf44bfb5,0x3fedbfb5,0x3fed0000,0xbf440000,0xbf444000,0x3fedc000,0xbf44bfb5,0xbfed3fb5,0x3fedbfb5,0x3f44bfb5,
0x3f153fb5,0xbf713fb5,0xbff53fb5,0xbfe23fb5,0x3fa2bffb,0x3e493ec8,0x3fc63ec8,0xbfff3ffb,0xbfff3f44,0x3fa2bf44,0x3e49bfed,0xbfc63fed,
0x3f713f8e,0x3ff5bfd5,0xbfe23fd5,0xbf153f8e,0xbfd50000,0xbec80000,0x3f8ec000,0x3ffbc000,0xbec83fed,0xbf8e3f44,0xbffb3f44,0x3fd5bfed,
0x3ffbbfb5,0xbfd53fb5,0x3ec83fb5,0x3f8ebfb5,0xbf8ebf44,0xbffb3fed,0x3fd5bfed,0x3ec8bf44,0x3fffbfb5,0x3fc6bfb5,0x3e493fb5,0xbfa23fb5,
0xbf15bf8e,0x3fe2bfd5,0x3ff5bfd5,0xbf713f8e,0xbfe23fed,0x3ff5bfed,0xbf71bf44,0xbf153f44,0x3fa23ec8,0x3fffbffb,0xbfc63ffb,0xbe493ec8,
0xc0004000,0xbfb54000,0x0,0x3fb50000,0xc0004000,0x3fb50000,0x0,0x3fb5c000,0xc0004000,0x3fb5c000,0x0,0xbfb50000,
0xc0004000,0xbfb50000,0x0,0xbfb54000,0x3fc6bfb5,0x3fffbfb5,0x3fa2bfb5,0xbe49bfb5,0x3fe2bfd5,0xbf15bf8e,0x3f71bf8e,0xbff53fd5,
0x3ff5bfed,0xbfe23fed,0x3f15bf44,0x3f713f44,0x3fffbffb,0x3fa23ec8,0x3e49bec8,0x3fc6bffb,0xbec80000,0xbfd50000,0xbffb4000,0xbf8e4000,
0xbf8e3f44,0xbec83fed,0xbfd53fed,0x3ffbbf44,0xbfd53fb5,0x3ffbbfb5,0xbf8e3fb5,0xbec8bfb5,0xbffb3fed,0xbf8ebf44,0xbec83f44,0xbfd53fed,
0xbf713fb5,0x3f153fb5,0x3fe2bfb5,0x3ff5bfb5,0x3e493ec8,0x3fa2bffb,0x3fffbffb,0xbfc6bec8,0x3fa2bf44,0xbfff3f44,0x3fc6bfed,0xbe493fed,
0x3ff5bfd5,0x3f713f8e,0x3f15bf8e,0x3fe2bfd5,0x3fedc000,0x3f44c000,0xbf440000,0xbfed0000,0x3f44bfb5,0xbfed3fb5,0xbfed3fb5,0x3f443fb5,
0xbf440000,0x3fed0000,0xbfed4000,0x3f44c000,0xbfed3fb5,0xbf44bfb5,0xbf443fb5,0xbfed3fb5,0xbff53fb5,0xbfe23fb5,0xbf153fb5,0x3f713fb5,
0xbfc63ffb,0x3fffbec8,0x3fa2bec8,0x3e49bffb,0x3e493f44,0xbfc6bf44,0x3fffbfed,0xbfa23fed,0x3fe2bf8e,0x3f153fd5,0x3f71bfd5,0x3ff5bf8e,
0x3f8e0000,0x3ffb0000,0x3fd5c000,0x3ec8c000,0x3ffbbfed,0xbfd5bf44,0xbec8bf44,0xbf8e3fed,0x3ec8bfb5,0x3f8e3fb5,0xbffb3fb5,0x3fd5bfb5,
0xbfd53f44,0xbec8bfed,0xbf8e3fed,0xbffb3f44,0x3e49bfb5,0xbfa2bfb5,0xbfff3fb5,0xbfc63fb5,0xbff53f8e,0x3f713fd5,0xbf153fd5,0x3fe2bf8e,
0xbf713fed,0xbf15bfed,0x3fe2bf44,0xbff53f44,0x3fc6bec8,0x3e493ffb,0x3fa2bffb,0x3fffbec8,0x4000,0x3fb54000,0x40000000,0x3fb50000,
0xc000,0xbfb50000,0xc0000000,0x3fb54000,0x4000,0xbfb5c000,0x40000000,0xbfb50000,0xc000,0x3fb50000,0xc0000000,0xbfb5c000,
0x3fa2bfb5,0xbe49bfb5,0xbfc6bfb5,0xbfffbfb5,0xbf713fd5,0x3ff53f8e,0x3fe23f8e,0xbf15bfd5,0x3f15bfed,0x3f713fed,0xbff5bf44,0x3fe23f44,
0xbe493ffb,0xbfc6bec8,0x3fff3ec8,0x3fa23ffb,0xbffb0000,0xbf8e0000,0x3ec84000,0x3fd54000,0x3fd5bf44,0xbffbbfed,0xbf8ebfed,0xbec83f44,
0xbf8e3fb5,0xbec8bfb5,0x3fd53fb5,0xbffbbfb5,0x3ec8bfed,0x3fd53f44,0xbffbbf44,0xbf8ebfed,0x3fe23fb5,0x3ff53fb5,0x3f71bfb5,0xbf15bfb5,
0xbfffbec8,0x3fc63ffb,0x3e493ffb,0x3fa23ec8,0x3fc6bf44,0xbe493f44,0xbfa2bfed,0x3fff3fed,0xbf153fd5,0xbfe2bf8e,0x3ff53f8e,0x3f713fd5,
0xbf44c000,0xbfedc000,0xbfed0000,0xbf440000,0x3fed3fb5,0xbf44bfb5,0x3f44bfb5,0xbfedbfb5,0xbfed0000,0x3f440000,0x3f444000,0xbfedc000,
0x3f44bfb5,0x3fed3fb5,0xbfedbfb5,0xbf44bfb5,0xbf153fb5,0x3f713fb5,0x3ff53fb5,0x3fe23fb5,0xbfa2bffb,0xbe493ec8,0xbfc63ec8,0x3fff3ffb,
0x3fff3f44,0xbfa2bf44,0xbe49bfed,0x3fc63fed,0xbf713f8e,0xbff5bfd5,0x3fe23fd5,0x3f153f8e,0x3fd50000,0x3ec80000,0xbf8ec000,0xbffbc000,
0x3ec83fed,0x3f8e3f44,0x3ffb3f44,0xbfd5bfed,0xbffbbfb5,0x3fd53fb5,0xbec83fb5,0xbf8ebfb5,0x3f8ebf44,0x3ffb3fed,0xbfd5bfed,0xbec8bf44,
0xbfffbfb5,0xbfc6bfb5,0xbe493fb5,0x3fa23fb5,0x3f15bf8e,0xbfe2bfd5,0xbff5bfd5,0x3f713f8e,0x3fe23fed,0xbff5bfed,0x3f71bf44,0x3f153f44,
0xbfa23ec8,0xbfffbffb,0x3fc63ffb,0x3e493ec8,0x80003f80,0x3f800000,0x80003f80,0x3f800000,0x80003f80,0x3f800000,0x80003f80,0x3f800000,
0x80003f80,0x3f800000,0x80003f80,0x3f800000,0x80003f80,0x3f800000,0x80003f80,0x3f800000,0x80003f80,0x3f800000,0x8000bf80,0xbf800000,
0x3f353f35,0x3f35bf35,0xbf35bf35,0xbf353f35,0x3f800000,0xbf80,0xbf800000,0x3f80,0x3f35bf35,0xbf35bf35,0xbf353f35,0x3f353f35,
0x80003f80,0x3f800000,0x80003f80,0x3f800000,0x3f800000,0xbf80,0x3f800000,0xbf80,0x8000bf80,0xbf800000,0x8000bf80,0xbf800000,
0xbf800000,0x3f80,0xbf800000,0x3f80,0x80003f80,0x3f800000,0x8000bf80,0xbf800000,0x3f35bf35,0xbf35bf35,0xbf353f35,0x3f353f35,
0xbf800000,0x3f80,0x3f800000,0xbf80,0x3f353f35,0x3f35bf35,0xbf35bf35,0xbf353f35,0x80003f80,0x3f800000,0x80003f80,0x3f800000,
0x8000bf80,0xbf800000,0x8000bf80,0xbf800000,0x80003f80,0x3f800000,0x80003f80,0x3f800000,0x8000bf80,0xbf800000,0x8000bf80,0xbf800000,
0x80003f80,0x3f800000,0x8000bf80,0xbf800000,0xbf35bf35,0xbf353f35,0x3f353f35,0x3f35bf35,0x3f800000,0xbf80,0xbf800000,0x3f80,
0xbf353f35,0x3f353f35,0x3f35bf35,0xbf35bf35,0x80003f80,0x3f800000,0x80003f80,0x3f800000,0xbf800000,0x3f80,0xbf800000,0x3f80,
0x8000bf80,0xbf800000,0x8000bf80,0xbf800000,0x3f800000,0xbf80,0x3f800000,0xbf80,0x80003f80,0x3f800000,0x8000bf80,0xbf800000,
0xbf353f35,0x3f353f35,0x3f35bf35,0xbf35bf35,0xbf800000,0x3f80,0x3f800000,0xbf80,0xbf35bf35,0xbf353f35,0x3f353f35,0x3f35bf35,
0x3f803f80,0x80008000,0x80008000,0xbf80bf80,0x3f803f80,0x80008000,0x80008000,0xbf80bf80,0x3f803f80,0x80008000,0x80008000,0xbf80bf80,
0x3f803f80,0x80008000,0x80008000,0xbf80bf80,0x3f353f80,0x3f358000,0x3f358000,0xbf35bf80,0xbf350000,0x3f353f80,0x3f353f80,0x3f358000,
0xbf35bf80,0xbf358000,0xbf358000,0x3f353f80,0x3f350000,0xbf35bf80,0xbf35bf80,0xbf358000,0x3f80,0x3f808000,0x3f808000,0x8000bf80,
0xbf80,0xbf808000,0xbf808000,0x80003f80,0x3f80,0x3f808000,0x3f808000,0x8000bf80,0xbf80,0xbf808000,0xbf808000,0x80003f80,
0xbf353f80,0x3f358000,0x3f358000,0x3f35bf80,0x3f350000,0x3f35bf80,0x3f35bf80,0xbf358000,0x3f35bf80,0xbf358000,0xbf358000,0xbf353f80,
0xbf350000,0xbf353f80,0xbf353f80,0x3f358000,0xbf803f80,0x80008000,0x80008000,0x3f80bf80,0xbf803f80,0x80008000,0x80008000,0x3f80bf80,
0xbf803f80,0x80008000,0x80008000,0x3f80bf80,0xbf803f80,0x80008000,0x80008000,0x3f80bf80,0xbf353f80,0xbf358000,0xbf358000,0x3f35bf80,
0x3f350000,0xbf353f80,0xbf353f80,0xbf358000,0x3f35bf80,0x3f358000,0x3f358000,0xbf353f80,0xbf350000,0x3f35bf80,0x3f35bf80,0x3f358000,
0x3f80,0xbf808000,0xbf808000,0x8000bf80,0xbf80,0x3f808000,0x3f808000,0x80003f80,0x3f80,0xbf808000,0xbf808000,0x8000bf80,
0xbf80,0x3f808000,0x3f808000,0x80003f80,0x3f353f80,0xbf358000,0xbf358000,0xbf35bf80,0xbf350000,0xbf35bf80,0xbf35bf80,0x3f358000,
0xbf35bf80,0x3f358000,0x3f358000,0x3f353f80,0x3f350000,0x3f353f80,0x3f353f80,0xbf358000,0x3f800000,0x0,0x3f800000,0x0,
0x3f800000,0x0,0x3f800000,0x0,0x3f800000,0x0,0x3f800000,0x0,0x3f800000,0x0,0x3f800000,0x0,
0x3f800000,0x0,0x3f7fb10f,0xbd48fb30,0x3f7ec46d,0xbdc8bd36,0x3f7d3aac,0xbe164083,0x3f7b14be,0xbe47c5c2,0x3f7853f8,0xbe78cfcc,
0x3f74fa0b,0xbe94a031,0x3f710908,0xbeac7cd4,0x3f800000,0x0,0x3f7ec46d,0xbdc8bd36,0x3f7b14be,0xbe47c5c2,0x3f74fa0b,0xbe94a031,
0x3f6c835e,0xbec3ef15,0x3f61c598,0xbef15aea,0x3f54db31,0xbf0e39da,0x3f45e403,0xbf226799,0x3f800000,0x0,0x3f7d3aac,0xbe164083,
0x3f74fa0b,0xbe94a031,0x3f676bd8,0xbedae880,0x3f54db31,0xbf0e39da,0x3f3daef9,0xbf2beb4a,0x3f226799,0xbf45e403,0x3f039c3d,0xbf5b941a,
0x3f800000,0x0,0x3f7b14be,0xbe47c5c2,0x3f6c835e,0xbec3ef15,0x3f54db31,0xbf0e39da,0x3f3504f3,0xbf3504f3,0x3f0e39da,0xbf54db31,
0x3ec3ef15,0xbf6c835e,0x3e47c5c2,0xbf7b14be,0x3f800000,0x0,0x3f7853f8,0xbe78cfcc,0x3f61c598,0xbef15aea,0x3f3daef9,0xbf2beb4a,
0x3f0e39da,0xbf54db31,0x3eac7cd4,0xbf710908,0x3dc8bd36,0xbf7ec46d,0xbe164083,0xbf7d3aac,0x3f800000,0x0,0x3f74fa0b,0xbe94a031,
0x3f54db31,0xbf0e39da,0x3f226799,0xbf45e403,0x3ec3ef15,0xbf6c835e,0x3dc8bd36,0xbf7ec46d,0xbe47c5c2,0xbf7b14be,0xbef15aea,0xbf61c598,
0x3f800000,0x0,0x3f710908,0xbeac7cd4,0x3f45e403,0xbf226799,0x3f039c3d,0xbf5b941a,0x3e47c5c2,0xbf7b14be,0xbe164083,0xbf7d3aac,
0xbef15aea,0xbf61c598,0xbf3daef9,0xbf2beb4a,0x3f800000,0x0,0x3f800000,0x0,0x3f800000,0x0,0x3f800000,0x0,
0x3f800000,0x0,0x3f800000,0x0,0x3f800000,0x0,0x3f800000,0x0,0x3f6c835e,0xbec3ef15,0x3f676bd8,0xbedae880,
0x3f61c598,0xbef15aea,0x3f5b941a,0xbf039c3d,0x3f54db31,0xbf0e39da,0x3f4d9f02,0xbf187fc0,0x3f45e403,0xbf226799,0x3f3daef9,0xbf2beb4a,
0x3f3504f3,0xbf3504f3,0x3f226799,0xbf45e403,0x3f0e39da,0xbf54db31,0x3ef15aea,0xbf61c598,0x3ec3ef15,0xbf6c835e,0x3e94a031,0xbf74fa0b,
0x3e47c5c2,0xbf7b14be,0x3dc8bd36,0xbf7ec46d,0x3ec3ef15,0xbf6c835e,0x3e78cfcc,0xbf7853f8,0x3dc8bd36,0xbf7ec46d,0xbd48fb30,0xbf7fb10f,
0xbe47c5c2,0xbf7b14be,0xbeac7cd4,0xbf710908,0xbef15aea,0xbf61c598,0xbf187fc0,0xbf4d9f02,0x0,0xbf800000,0xbe47c5c2,0xbf7b14be,
0xbec3ef15,0xbf6c835e,0xbf0e39da,0xbf54db31,0xbf3504f3,0xbf3504f3,0xbf54db31,0xbf0e39da,0xbf6c835e,0xbec3ef15,0xbf7b14be,0xbe47c5c2,
0xbec3ef15,0xbf6c835e,0xbf187fc0,0xbf4d9f02,0xbf45e403,0xbf226799,0xbf676bd8,0xbedae880,0xbf7b14be,0xbe47c5c2,0xbf7fb10f,0x3d48fb30,
0xbf74fa0b,0x3e94a031,0xbf5b941a,0x3f039c3d,0xbf3504f3,0xbf3504f3,0xbf61c598,0xbef15aea,0xbf7b14be,0xbe47c5c2,0xbf7ec46d,0x3dc8bd36,
0xbf6c835e,0x3ec3ef15,0xbf45e403,0x3f226799,0xbf0e39da,0x3f54db31,0xbe94a031,0x3f74fa0b,0xbf6c835e,0xbec3ef15,0xbf7fb10f,0xbd48fb30,
0xbf74fa0b,0x3e94a031,0xbf4d9f02,0x3f187fc0,0xbf0e39da,0x3f54db31,0xbe78cfcc,0x3f7853f8,0x3dc8bd36,0x3f7ec46d,0x3edae880,0x3f676bd8,
0x80003f80,0x3f800000,0x3f800000,0xbf80,0x3ec43f6d,0x3f6dbec4,0x3f6dbec4,0xbec4bf6d,0x3f353f35,0x3f35bf35,0x3f35bf35,0xbf35bf35,
0x3f6d3ec4,0x3ec4bf6d,0x3ec4bf6d,0xbf6dbec4,0x80003f80,0x3f800000,0xbf800000,0x3f80,0x3f6d3ec4,0x3ec4bf6d,0xbec43f6d,0x3f6d3ec4,
0x3f35bf35,0xbf35bf35,0x3f353f35,0x3f35bf35,0xbec4bf6d,0xbf6d3ec4,0x3f6dbec4,0xbec4bf6d,0x80003f80,0x3f800000,0x3f800000,0xbf80,
0x3f6dbec4,0xbec4bf6d,0xbec4bf6d,0xbf6d3ec4,0xbf35bf35,0xbf353f35,0xbf353f35,0x3f353f35,0xbec43f6d,0x3f6d3ec4,0x3f6d3ec4,0x3ec4bf6d,
0x80003f80,0x3f800000,0xbf800000,0x3f80,0x3ec4bf6d,0xbf6dbec4,0x3f6d3ec4,0x3ec4bf6d,0xbf353f35,0x3f353f35,0xbf35bf35,0xbf353f35,
0x3f6dbec4,0xbec4bf6d,0x3ec43f6d,0x3f6dbec4,0x80003f80,0x3f800000,0x3f800000,0xbf80,0xbec4bf6d,0xbf6d3ec4,0xbf6d3ec4,0x3ec43f6d,
0x3f353f35,0x3f35bf35,0x3f35bf35,0xbf35bf35,0xbf6dbec4,0xbec43f6d,0xbec43f6d,0x3f6d3ec4,0x80003f80,0x3f800000,0xbf800000,0x3f80,
0xbf6dbec4,0xbec43f6d,0x3ec4bf6d,0xbf6dbec4,0x3f35bf35,0xbf35bf35,0x3f353f35,0x3f35bf35,0x3ec43f6d,0x3f6dbec4,0xbf6d3ec4,0x3ec43f6d,
0x80003f80,0x3f800000,0x3f800000,0xbf80,0xbf6d3ec4,0x3ec43f6d,0x3ec43f6d,0x3f6dbec4,0xbf35bf35,0xbf353f35,0xbf353f35,0x3f353f35,
0x3ec4bf6d,0xbf6dbec4,0xbf6dbec4,0xbec43f6d,0x80003f80,0x3f800000,0xbf800000,0x3f80,0xbec43f6d,0x3f6d3ec4,0xbf6dbec4,0xbec43f6d,
0xbf353f35,0x3f353f35,0xbf35bf35,0xbf353f35,0xbf6d3ec4,0x3ec43f6d,0xbec4bf6d,0xbf6d3ec4,0x3f803f80,0x80008000,0x80008000,0xbf80bf80,
0x3f803f80,0x80008000,0x80008000,0xbf80bf80,0x3f803f80,0x80008000,0x80008000,0xbf80bf80,0x3f803f80,0x80008000,0x80008000,0xbf80bf80,
0x3ec43f6d,0x3f6d3ec4,0x3f6d3ec4,0xbec4bf6d,0xbf6dbec4,0x3ec43f6d,0x3ec43f6d,0x3f6d3ec4,0xbec4bf6d,0xbf6dbec4,0xbf6dbec4,0x3ec43f6d,
0x3f6d3ec4,0xbec4bf6d,0xbec4bf6d,0xbf6dbec4,0xbf353f35,0x3f353f35,0x3f353f35,0x3f35bf35,0x3f35bf35,0xbf35bf35,0xbf35bf35,0xbf353f35,
0xbf353f35,0x3f353f35,0x3f353f35,0x3f35bf35,0x3f35bf35,0xbf35bf35,0xbf35bf35,0xbf353f35,0xbf6d3ec4,0xbec43f6d,0xbec43f6d,0x3f6dbec4,
0xbec43f6d,0x3f6dbec4,0x3f6dbec4,0x3ec4bf6d,0x3f6dbec4,0x3ec4bf6d,0x3ec4bf6d,0xbf6d3ec4,0x3ec4bf6d,0xbf6d3ec4,0xbf6d3ec4,0xbec43f6d,
0x0,0xbf803f80,0xbf803f80,0x80008000,0x0,0xbf803f80,0xbf803f80,0x80008000,0x0,0xbf803f80,0xbf803f80,0x80008000,
0x0,0xbf803f80,0xbf803f80,0x80008000,0x3f6dbec4,0xbec43f6d,0xbec43f6d,0xbf6d3ec4,0x3ec4bf6d,0x3f6dbec4,0x3f6dbec4,0xbec43f6d,
0xbf6d3ec4,0x3ec4bf6d,0x3ec4bf6d,0x3f6dbec4,0xbec43f6d,0xbf6d3ec4,0xbf6d3ec4,0x3ec4bf6d,0x3f35bf35,0x3f353f35,0x3f353f35,0xbf353f35,
0xbf353f35,0xbf35bf35,0xbf35bf35,0x3f35bf35,0x3f35bf35,0x3f353f35,0x3f353f35,0xbf353f35,0xbf353f35,0xbf35bf35,0xbf35bf35,0x3f35bf35,
0xbec4bf6d,0x3f6d3ec4,0x3f6d3ec4,0x3ec43f6d,0x3f6d3ec4,0x3ec43f6d,0x3ec43f6d,0xbf6dbec4,0x3ec43f6d,0xbf6dbec4,0xbf6dbec4,0xbec4bf6d,
0xbf6dbec4,0xbec4bf6d,0xbec4bf6d,0x3f6d3ec4,0x3f800000,0x0,0x3f7fec43,0xbcc90ab0,0x3f7fb10f,0xbd48fb30,0x3f7f4e6d,0xbd96a905,
0x3f7ec46d,0xbdc8bd36,0x3f7e1324,0xbdfab273,0x3f7d3aac,0xbe164083,0x3f7c3b28,0xbe2f10a2,0x3f800000,0x0,0x3f7f4e6d,0xbd96a905,
0x3f7d3aac,0xbe164083,0x3f79c79d,0xbe605c13,0x3f74fa0b,0xbe94a031,0x3f6ed89e,0xbeb8442a,0x3f676bd8,0xbedae880,0x3f5ebe05,0xbefc5d27,
0x3f800000,0x0,0x3f7e1324,0xbdfab273,0x3f7853f8,0xbe78cfcc,0x3f6ed89e,0xbeb8442a,0x3f61c598,0xbef15aea,0x3f514d3d,0xbf13682a,
0x3f3daef9,0xbf2beb4a,0x3f273656,0xbf41d870,0x3f800000,0x0,0x3f7c3b28,0xbe2f10a2,0x3f710908,0xbeac7cd4,0x3f5ebe05,0xbefc5d27,
0x3f45e403,0xbf226799,0x3f273656,0xbf41d870,0x3f039c3d,0xbf5b941a,0x3eb8442a,0xbf6ed89e,0x3f800000,0x0,0x3f79c79d,0xbe605c13,
0x3f676bd8,0xbedae880,0x3f49d112,0xbf1d7fd1,0x3f226799,0xbf45e403,0x3ee63375,0xbf64aa59,0x3e78cfcc,0xbf7853f8,0x3cc90ab0,0xbf7fec43,
0x3f800000,0x0,0x3f76ba07,0xbe888e93,0x3f5b941a,0xbf039c3d,0x3f3085bb,0xbf396842,0x3ef15aea,0xbf61c598,0x3e605c13,0xbf79c79d,
0xbd48fb30,0xbf7fb10f,0xbea09ae5,0xbf731447,0x3f800000,0x0,0x3f731447,0xbea09ae5,0x3f4d9f02,0xbf187fc0,0x3f13682a,0xbf514d3d,
0x3e94a031,0xbf74fa0b,0xbcc90ab0,0xbf7fec43,0xbeac7cd4,0xbf710908,0xbf1d7fd1,0xbf49d112,0x3f800000,0x0,0x3f6ed89e,0xbeb8442a,
0x3f3daef9,0xbf2beb4a,0x3ee63375,0xbf64aa59,0x3dc8bd36,0xbf7ec46d,0xbe888e93,0xbf76ba07,0xbf187fc0,0xbf4d9f02,0xbf584853,0xbf08f59b,
0x3f7b14be,0xbe47c5c2,0x3f79c79d,0xbe605c13,0x3f7853f8,0xbe78cfcc,0x3f76ba07,0xbe888e93,0x3f74fa0b,0xbe94a031,0x3f731447,0xbea09ae5,
0x3f710908,0xbeac7cd4,0x3f6ed89e,0xbeb8442a,0x3f54db31,0xbf0e39da,0x3f49d112,0xbf1d7fd1,0x3f3daef9,0xbf2beb4a,0x3f3085bb,0xbf396842,
0x3f226799,0xbf45e403,0x3f13682a,0xbf514d3d,0x3f039c3d,0xbf5b941a,0x3ee63375,0xbf64aa59,0x3f0e39da,0xbf54db31,0x3ee63375,0xbf64aa59,
0x3eac7cd4,0xbf710908,0x3e605c13,0xbf79c79d,0x3dc8bd36,0xbf7ec46d,0xbcc90ab0,0xbf7fec43,0xbe164083,0xbf7d3aac,0xbe888e93,0xbf76ba07,
0x3e47c5c2,0xbf7b14be,0x3cc90ab0,0xbf7fec43,0xbe164083,0xbf7d3aac,0xbea09ae5,0xbf731447,0xbef15aea,0xbf61c598,0xbf1d7fd1,0xbf49d112,
0xbf3daef9,0xbf2beb4a,0xbf584853,0xbf08f59b,0xbe47c5c2,0xbf7b14be,0xbecf7bca,0xbf6a09a7,0xbf187fc0,0xbf4d9f02,0xbf41d870,0xbf273656,
0xbf61c598,0xbef15aea,0xbf76ba07,0xbe888e93,0xbf7fb10f,0xbd48fb30,0xbf7c3b28,0x3e2f10a2,0xbf0e39da,0xbf54db31,0xbf41d870,0xbf273656,
0xbf676bd8,0xbedae880,0xbf7c3b28,0xbe2f10a2,0xbf7ec46d,0x3dc8bd36,0xbf6ed89e,0x3eb8442a,0xbf4d9f02,0x3f187fc0,0xbf1d7fd1,0x3f49d112,
0xbf54db31,0xbf0e39da,0xbf76ba07,0xbe888e93,0xbf7fb10f,0x3d48fb30,0xbf6ed89e,0x3eb8442a,0xbf45e403,0x3f226799,0xbf08f59b,0x3f584853,
0xbe78cfcc,0x3f7853f8,0x3d96a905,0x3f7f4e6d,0xbf7b14be,0xbe47c5c2,0xbf7c3b28,0x3e2f10a2,0xbf5b941a,0x3f039c3d,0xbf1d7fd1,0x3f49d112,
0xbe94a031,0x3f74fa0b,0x3d96a905,0x3f7f4e6d,0x3edae880,0x3f676bd8,0x3f396842,0x3f3085bb,0x80003f80,0x80003f80,0x80003f80,0x80003f80,
0x80003f80,0x80003f80,0x80003f80,0x80003f80,0x80003f80,0x80003f80,0x80003f80,0x80003f80,0x80003f80,0x80003f80,0x80003f80,0x80003f80,
0x3f800000,0x3f800000,0x3f800000,0x3f800000,0x3f800000,0x3f800000,0x3f800000,0x3f800000,0x3f800000,0x3f800000,0x3f800000,0x3f800000,
0x3f800000,0x3f800000,0x3f800000,0x3f800000,0x80003f80,0x3f353f35,0x80003f80,0x3f353f35,0x3f800000,0x3f35bf35,0x3f800000,0x3f35bf35,
0x8000bf80,0xbf35bf35,0x8000bf80,0xbf35bf35,0xbf800000,0xbf353f35,0xbf800000,0xbf353f35,0x3f800000,0x3f35bf35,0x3f800000,0x3f35bf35,
0xbf80,0xbf35bf35,0xbf80,0xbf35bf35,0xbf800000,0xbf353f35,0xbf800000,0xbf353f35,0x3f80,0x3f353f35,0x3f80,0x3f353f35,
0x80003f80,0x3f800000,0x80003f80,0x3f800000,0x8000bf80,0xbf800000,0x8000bf80,0xbf800000,0x80003f80,0x3f800000,0x80003f80,0x3f800000,
0x8000bf80,0xbf800000,0x8000bf80,0xbf800000,0x3f800000,0xbf80,0x3f800000,0xbf80,0xbf800000,0x3f80,0xbf800000,0x3f80,
0x3f800000,0xbf80,0x3f800000,0xbf80,0xbf800000,0x3f80,0xbf800000,0x3f80,0x80003f80,0x3f35bf35,0x80003f80,0x3f35bf35,
0xbf800000,0x3f353f35,0xbf800000,0x3f353f35,0x8000bf80,0xbf353f35,0x8000bf80,0xbf353f35,0x3f800000,0xbf35bf35,0x3f800000,0xbf35bf35,
0x3f800000,0xbf35bf35,0x3f800000,0xbf35bf35,0x3f80,0x3f35bf35,0x3f80,0x3f35bf35,0xbf800000,0x3f353f35,0xbf800000,0x3f353f35,
0xbf80,0xbf353f35,0xbf80,0xbf353f35,0x80003f80,0x3ec43f6d,0x8000bf80,0xbec4bf6d,0x3f353f35,0x3f6d3ec4,0xbf35bf35,0xbf6dbec4,
0x3f800000,0x3f6dbec4,0xbf800000,0xbf6d3ec4,0x3f35bf35,0x3ec4bf6d,0xbf353f35,0xbec43f6d,0x3f800000,0x3f6dbec4,0xbf800000,0xbf6d3ec4,
0x3f35bf35,0x3ec4bf6d,0xbf353f35,0xbec43f6d,0xbf80,0xbec4bf6d,0x3f80,0x3ec43f6d,0xbf35bf35,0xbf6dbec4,0x3f353f35,0x3f6d3ec4,
0x80003f80,0x3f6d3ec4,0x8000bf80,0xbf6dbec4,0x3f35bf35,0xbec4bf6d,0xbf353f35,0x3ec43f6d,0xbf800000,0xbec43f6d,0x3f800000,0x3ec4bf6d,
0x3f353f35,0x3f6dbec4,0xbf35bf35,0xbf6d3ec4,0x3f800000,0x3ec4bf6d,0xbf800000,0xbec43f6d,0xbf35bf35,0xbf6d3ec4,0x3f353f35,0x3f6dbec4,
0x3f80,0x3f6d3ec4,0xbf80,0xbf6dbec4,0x3f35bf35,0xbec4bf6d,0xbf353f35,0x3ec43f6d,0x80003f80,0x3f6dbec4,0x8000bf80,0xbf6d3ec4,
0xbf35bf35,0xbec43f6d,0x3f353f35,0x3ec4bf6d,0x3f800000,0xbec4bf6d,0xbf800000,0x3ec43f6d,0xbf353f35,0x3f6d3ec4,0x3f35bf35,0xbf6dbec4,
0x3f800000,0xbec4bf6d,0xbf800000,0x3ec43f6d,0xbf353f35,0x3f6d3ec4,0x3f35bf35,0xbf6dbec4,0xbf80,0xbf6d3ec4,0x3f80,0x3f6dbec4,
0x3f353f35,0x3ec4bf6d,0xbf35bf35,0xbec43f6d,0x80003f80,0x3ec4bf6d,0x8000bf80,0xbec43f6d,0xbf353f35,0x3f6dbec4,0x3f35bf35,0xbf6d3ec4,
0xbf800000,0x3f6d3ec4,0x3f800000,0xbf6dbec4,0xbf35bf35,0x3ec43f6d,0x3f353f35,0xbec4bf6d,0x3f800000,0xbf6dbec4,0xbf800000,0x3f6d3ec4,
0x3f353f35,0xbec4bf6d,0xbf35bf35,0x3ec43f6d,0x3f80,0x3ec4bf6d,0xbf80,0xbec43f6d,0xbf353f35,0x3f6dbec4,0x3f35bf35,0xbf6d3ec4,
0x80003f80,0x8000bf80,0x80003f80,0x8000bf80,0x80003f80,0x8000bf80,0x80003f80,0x8000bf80,0x80003f80,0x8000bf80,0x80003f80,0x8000bf80,
0x80003f80,0x8000bf80,0x80003f80,0x8000bf80,0x3f800000,0xbf800000,0x3f800000,0xbf800000,0x3f800000,0xbf800000,0x3f800000,0xbf800000,
0x3f800000,0xbf800000,0x3f800000,0xbf800000,0x3f800000,0xbf800000,0x3f800000,0xbf800000,0x80003f80,0xbf35bf35,0x80003f80,0xbf35bf35,
0x3f800000,0xbf353f35,0x3f800000,0xbf353f35,0x8000bf80,0x3f353f35,0x8000bf80,0x3f353f35,0xbf800000,0x3f35bf35,0xbf800000,0x3f35bf35,
0x3f800000,0xbf353f35,0x3f800000,0xbf353f35,0xbf80,0x3f353f35,0xbf80,0x3f353f35,0xbf800000,0x3f35bf35,0xbf800000,0x3f35bf35,
0x3f80,0xbf35bf35,0x3f80,0xbf35bf35,0x80003f80,0xbf800000,0x80003f80,0xbf800000,0x8000bf80,0x3f800000,0x8000bf80,0x3f800000,
0x80003f80,0xbf800000,0x80003f80,0xbf800000,0x8000bf80,0x3f800000,0x8000bf80,0x3f800000,0x3f800000,0x3f80,0x3f800000,0x3f80,
0xbf800000,0xbf80,0xbf800000,0xbf80,0x3f800000,0x3f80,0x3f800000,0x3f80,0xbf800000,0xbf80,0xbf800000,0xbf80,
0x80003f80,0xbf353f35,0x80003f80,0xbf353f35,0xbf800000,0xbf35bf35,0xbf800000,0xbf35bf35,0x8000bf80,0x3f35bf35,0x8000bf80,0x3f35bf35,
0x3f800000,0x3f353f35,0x3f800000,0x3f353f35,0x3f800000,0x3f353f35,0x3f800000,0x3f353f35,0x3f80,0xbf353f35,0x3f80,0xbf353f35,
0xbf800000,0xbf35bf35,0xbf800000,0xbf35bf35,0xbf80,0x3f35bf35,0xbf80,0x3f35bf35,0x80003f80,0xbec4bf6d,0x8000bf80,0x3ec43f6d,
0x3f353f35,0xbf6dbec4,0xbf35bf35,0x3f6d3ec4,0x3f800000,0xbf6d3ec4,0xbf800000,0x3f6dbec4,0x3f35bf35,0xbec43f6d,0xbf353f35,0x3ec4bf6d,
0x3f800000,0xbf6d3ec4,0xbf800000,0x3f6dbec4,0x3f35bf35,0xbec43f6d,0xbf353f35,0x3ec4bf6d,0xbf80,0x3ec43f6d,0x3f80,0xbec4bf6d,
0xbf35bf35,0x3f6d3ec4,0x3f353f35,0xbf6dbec4,0x80003f80,0xbf6dbec4,0x8000bf80,0x3f6d3ec4,0x3f35bf35,0x3ec43f6d,0xbf353f35,0xbec4bf6d,
0xbf800000,0x3ec4bf6d,0x3f800000,0xbec43f6d,0x3f353f35,0xbf6d3ec4,0xbf35bf35,0x3f6dbec4,0x3f800000,0xbec43f6d,0xbf800000,0x3ec4bf6d,
0xbf35bf35,0x3f6dbec4,0x3f353f35,0xbf6d3ec4,0x3f80,0xbf6dbec4,0xbf80,0x3f6d3ec4,0x3f35bf35,0x3ec43f6d,0xbf353f35,0xbec4bf6d,
0x80003f80,0xbf6d3ec4,0x8000bf80,0x3f6dbec4,0xbf35bf35,0x3ec4bf6d,0x3f353f35,0xbec43f6d,0x3f800000,0x3ec43f6d,0xbf800000,0xbec4bf6d,
0xbf353f35,0xbf6dbec4,0x3f35bf35,0x3f6d3ec4,0x3f800000,0x3ec43f6d,0xbf800000,0xbec4bf6d,0xbf353f35,0xbf6dbec4,0x3f35bf35,0x3f6d3ec4,
0xbf80,0x3f6dbec4,0x3f80,0xbf6d3ec4,0x3f353f35,0xbec43f6d,0xbf35bf35,0x3ec4bf6d,0x80003f80,0xbec43f6d,0x8000bf80,0x3ec4bf6d,
0xbf353f35,0xbf6d3ec4,0x3f35bf35,0x3f6dbec4,0xbf800000,0xbf6dbec4,0x3f800000,0x3f6d3ec4,0xbf35bf35,0xbec4bf6d,0x3f353f35,0x3ec43f6d,
0x3f800000,0x3f6d3ec4,0xbf800000,0xbf6dbec4,0x3f353f35,0x3ec43f6d,0xbf35bf35,0xbec4bf6d,0x3f80,0xbec43f6d,0xbf80,0x3ec4bf6d,
0xbf353f35,0xbf6d3ec4,0x3f35bf35,0x3f6dbec4,
};
constexpr int TB_F = 0, TB_E = 512, TB_P2 = 1024;

enum { C_EP = 0, C_Z1 = 32, C_Z2 = 96, C_H3 = 128, C_U = 160, C_X = 288, C_TOTAL = 512 };
struct Scratch {
  unsigned cnt[C_TOTAL];
  uint32_t moda[8 * 2 * D_];
  uint32_t mod[4 * D_ + 256];
  uint32_t z1[120 * 5120];
  uint32_t z2[128 * 4800];
  uint8_t h3[32 * 18 * 4096];
  uint8_t u[72 * D_ * 128];
};
__device__ __align__(1024) Scratch g_s;

constexpr int HOLDA = 5;
constexpr int X1K = 10;
constexpr int NV1 = 12;
constexpr int NV2 = 20;
constexpr int W0N = 3;
constexpr int TRK0 = 50;
constexpr int TRKC = 350;
constexpr int HD1 = 150;
constexpr int EH = 7;

struct Maps { CUtensorMap z1, z2[2], w1a, w1b, h3, w2, wf[4], wm; };
struct Params {
  const __nv_bfloat16 *x, *c, *wmod;
  Scratch* s;
  const uint4* tab;
  const __nv_bfloat16 *wr, *wi, *w1, *w2, *b1, *b2;
  uint32_t* out;
};

__device__ __forceinline__ uint32_t smem_u32(const void* p) { return (uint32_t)__cvta_generic_to_shared(p); }
__device__ __forceinline__ void mbar_init(uint32_t b, int c) { asm volatile("mbarrier.init.shared::cta.b64 [%0], %1;" ::"r"(b), "r"(c)); }
__device__ __forceinline__ void mbar_expect(uint32_t b, int bytes) { asm volatile("mbarrier.arrive.expect_tx.shared::cta.b64 _, [%0], %1;" ::"r"(b), "r"(bytes) : "memory"); }
__device__ __forceinline__ void mbar_arrive(uint32_t b) { asm volatile("mbarrier.arrive.shared::cta.b64 _, [%0];" ::"r"(b) : "memory"); }
__device__ __forceinline__ void mbar_wait(uint32_t b, int ph) {
  asm volatile("{\n.reg .pred p;\n.reg .u32 it;\nmov.u32 it, 0;\nW:\nmbarrier.try_wait.parity.shared::cta.b64 p, [%0], %1;\n"
               "@p bra.uni D;\nadd.u32 it, it, 1;\nsetp.lt.u32 p, it, 0x400000;\n@p bra.uni W;\ntrap;\nD:\n}" ::"r"(b), "r"(ph) : "memory");
}
__device__ __forceinline__ uint32_t mbar_test(uint32_t b, int ph) {
  uint32_t ok;
  asm volatile("{\n.reg .pred p;\nmbarrier.test_wait.parity.shared::cta.b64 p, [%1], %2;\nselp.u32 %0, 1, 0, p;\n}\n" : "=r"(ok) : "r"(b), "r"(ph) : "memory");
  return ok;
}
__device__ __forceinline__ void tma2d(uint32_t dst, const CUtensorMap* m, int c0, int c1, uint32_t bar) {
  asm volatile("cp.async.bulk.tensor.2d.shared::cluster.global.mbarrier::complete_tx::bytes [%0], [%1, {%3, %4}], [%2];" ::"r"(dst), "l"(m), "r"(bar), "r"(c0), "r"(c1) : "memory");
}
__device__ __forceinline__ uint64_t pol_ef() { uint64_t p; asm("createpolicy.fractional.L2::evict_first.b64 %0, 1.0;" : "=l"(p)); return p; }
__device__ __forceinline__ void tma3d_ef(uint32_t dst, const CUtensorMap* m, int c1, int c2, uint32_t bar) {
  asm volatile("cp.async.bulk.tensor.3d.shared::cluster.global.mbarrier::complete_tx::bytes.L2::cache_hint [%0], [%1, {%3, %4, %5}], [%2], %6;" ::"r"(dst), "l"(m), "r"(bar), "r"(0), "r"(c1), "r"(c2), "l"(pol_ef()) : "memory");
}
__device__ __forceinline__ void tma4d_ef(uint32_t dst, const CUtensorMap* m, int c1, int c2, int c3, uint32_t bar) {
  asm volatile("cp.async.bulk.tensor.4d.shared::cluster.global.mbarrier::complete_tx::bytes.L2::cache_hint [%0], [%1, {%3, %7, %4, %5}], [%2], %6;" ::"r"(dst), "l"(m), "r"(bar), "r"(0), "r"(c2), "r"(c3), "l"(pol_ef()), "r"(c1) : "memory");
}
__device__ __forceinline__ void bulk_ld(uint32_t dst, const void* src, int bytes, uint32_t bar) {
  asm volatile("cp.async.bulk.shared::cluster.global.mbarrier::complete_tx::bytes [%0], [%1], %2, [%3];" ::"r"(dst), "l"(src), "r"(bytes), "r"(bar) : "memory");
}
__device__ __forceinline__ void bulk_st(void* dst, uint32_t src, int bytes) {
  asm volatile("cp.async.bulk.global.shared::cta.bulk_group [%0], [%1], %2;" ::"l"(dst), "r"(src), "r"(bytes) : "memory");
}
__device__ __forceinline__ void tma_st2d(const CUtensorMap* m, uint32_t src, int c0, int c1) {
  asm volatile("cp.async.bulk.tensor.2d.global.shared::cta.bulk_group [%0, {%2, %3}], [%1];" ::"l"(m), "r"(src), "r"(c0), "r"(c1) : "memory");
}
__device__ __forceinline__ void tma_st3d(const CUtensorMap* m, uint32_t src, int c0, int c1, int c2) {
  asm volatile("cp.async.bulk.tensor.3d.global.shared::cta.bulk_group [%0, {%2, %3, %4}], [%1];" ::"l"(m), "r"(src), "r"(c0), "r"(c1), "r"(c2) : "memory");
}
__device__ __forceinline__ void bulk_commit_wait() {
  asm volatile("cp.async.bulk.commit_group;" ::: "memory");
  asm volatile("cp.async.bulk.wait_group 0;" ::: "memory");
}
__device__ __forceinline__ void prefetch_l2(const void* p, int bytes) {
  asm volatile("cp.async.bulk.prefetch.L2.global [%0], %1;" ::"l"(p), "r"(bytes) : "memory");
}
__device__ __forceinline__ void wg_fence() { asm volatile("wgmma.fence.sync.aligned;" ::: "memory"); }
__device__ __forceinline__ void wg_commit() { asm volatile("wgmma.commit_group.sync.aligned;" ::: "memory"); }
template <int N> __device__ __forceinline__ void wg_wait() { asm volatile("wgmma.wait_group.sync.aligned %0;" ::"n"(N) : "memory"); }
template <int N> __device__ __forceinline__ void reg_fence(float (&d)[N]) {
#pragma unroll
  for (int i = 0; i < N; i++) asm volatile("" : "+f"(d[i])::"memory");
}
__device__ __forceinline__ void fence_async_smem() { asm volatile("fence.proxy.async.shared::cta;" ::: "memory"); }
__device__ __forceinline__ void fence_async_glb() { asm volatile("fence.proxy.async.global;" ::: "memory"); }
__device__ __forceinline__ uint32_t ld_rlx(const void* p) { uint32_t v; asm volatile("ld.relaxed.gpu.global.b32 %0, [%1];" : "=r"(v) : "l"(p) : "memory"); return v; }
__device__ __forceinline__ uint2 ld_rlx2(const void* p) { uint2 v; asm volatile("ld.relaxed.gpu.global.v2.b32 {%0,%1}, [%2];" : "=r"(v.x), "=r"(v.y) : "l"(p) : "memory"); return v; }
__device__ __forceinline__ uint4 ld_rlx4(const void* p) { uint4 v; asm volatile("ld.relaxed.gpu.global.v4.b32 {%0,%1,%2,%3}, [%4];" : "=r"(v.x), "=r"(v.y), "=r"(v.z), "=r"(v.w) : "l"(p) : "memory"); return v; }
__device__ __forceinline__ uint32_t ld_nc(const void* p) { uint32_t v; asm volatile("ld.global.nc.L1::no_allocate.b32 %0, [%1];" : "=r"(v) : "l"(p) : "memory"); return v; }
__device__ __forceinline__ uint4 ld_nc4(const void* p) { uint4 v; asm volatile("ld.global.nc.v4.b32 {%0,%1,%2,%3}, [%4];" : "=r"(v.x), "=r"(v.y), "=r"(v.z), "=r"(v.w) : "l"(p) : "memory"); return v; }
__device__ __forceinline__ uint32_t lds(uint32_t a) { uint32_t v; asm volatile("ld.shared.b32 %0, [%1];" : "=r"(v) : "r"(a) : "memory"); return v; }
__device__ __forceinline__ uint2 lds2(uint32_t a) { uint2 v; asm volatile("ld.shared.v2.b32 {%0,%1}, [%2];" : "=r"(v.x), "=r"(v.y) : "r"(a) : "memory"); return v; }
__device__ __forceinline__ void lds2_if(int on, uint2& v, uint32_t a) { asm volatile("{\n.reg .pred p;\nsetp.ne.u32 p, %3, 0;\n@p ld.shared.v2.b32 {%0,%1}, [%2];\n}" : "+r"(v.x), "+r"(v.y) : "r"(a), "r"(on) : "memory"); }
__device__ __forceinline__ uint4 lds4(uint32_t a) { uint4 v; asm volatile("ld.shared.v4.b32 {%0,%1,%2,%3}, [%4];" : "=r"(v.x), "=r"(v.y), "=r"(v.z), "=r"(v.w) : "r"(a) : "memory"); return v; }
__device__ __forceinline__ float lds_bf(uint32_t a) { uint32_t v; asm volatile("ld.shared.u16 %0, [%1];" : "=r"(v) : "r"(a) : "memory"); return __uint_as_float(v << 16); }
__device__ __forceinline__ void sts(uint32_t a, uint32_t v) { asm volatile("st.shared.b32 [%0], %1;" ::"r"(a), "r"(v) : "memory"); }
__device__ __forceinline__ void sts2(uint32_t a, uint32_t v0, uint32_t v1) { asm volatile("st.shared.v2.b32 [%0], {%1,%2};" ::"r"(a), "r"(v0), "r"(v1) : "memory"); }
__device__ __forceinline__ void sts4(uint32_t a, uint32_t v0, uint32_t v1, uint32_t v2, uint32_t v3) { asm volatile("st.shared.v4.b32 [%0], {%1,%2,%3,%4};" ::"r"(a), "r"(v0), "r"(v1), "r"(v2), "r"(v3) : "memory"); }
__device__ __forceinline__ void bar_sync(int id, int n) { asm volatile("bar.sync %0, %1;" ::"r"(id), "r"(n) : "memory"); }
__device__ __forceinline__ void bar_arrive(int id, int n) { asm volatile("bar.arrive %0, %1;" ::"r"(id), "r"(n) : "memory"); }
__device__ __forceinline__ void red_add(unsigned* p, unsigned v) { asm volatile("red.relaxed.gpu.global.add.u32 [%0], %1;" ::"l"(p), "r"(v) : "memory"); }
__device__ __forceinline__ bool any(bool p) { return __any_sync(0xffffffffu, p); }
__device__ __forceinline__ void pause(unsigned clks) {
  asm volatile("{\n.reg .pred p;\n.reg .u32 a, b;\nmov.u32 a, %%clock;\nW:\nmov.u32 b, %%clock;\nsub.u32 b, b, a;\nsetp.lt.s32 p, b, %0;\n@p bra.uni W;\n}" ::"r"(clks) : "memory");
}
__device__ __forceinline__ void red_bf16x8(uint32_t* p, uint32_t a, uint32_t b, uint32_t c, uint32_t d) {
  asm volatile("red.relaxed.gpu.global.add.noftz.v4.bf16x2 [%0], {%1,%2,%3,%4};" ::"l"(p), "r"(a), "r"(b), "r"(c), "r"(d) : "memory");
}
__device__ __forceinline__ void red_bf16x4(uint32_t* p, uint32_t a, uint32_t b) {
  asm volatile("red.relaxed.gpu.global.add.noftz.v2.bf16x2 [%0], {%1,%2};" ::"l"(p), "r"(a), "r"(b) : "memory");
}
constexpr int SPIN_MAX = 1 << 20;
__device__ __forceinline__ uint32_t ld_acq(const void* p) { uint32_t v; asm volatile("ld.acquire.gpu.global.b32 %0, [%1];" : "=r"(v) : "l"(p) : "memory"); return v; }
template <bool ACQ = false> __device__ __forceinline__ void wait_cnt(const unsigned* p, unsigned target) {
  int it = 0;
  while (any((int)((ACQ ? ld_acq(p) : ld_rlx(p)) - target) < 0) && ++it < SPIN_MAX) {}
}
__device__ __forceinline__ uint32_t pack_bf16(float lo, float hi) { uint32_t r; asm("cvt.rn.bf16x2.f32 %0, %1, %2;" : "=r"(r) : "f"(hi), "f"(lo)); return r; }
__device__ __forceinline__ float bf_lo(uint32_t v) { return __uint_as_float(v << 16); }
__device__ __forceinline__ float bf_hi(uint32_t v) { return __uint_as_float(v & 0xffff0000u); }
__device__ __forceinline__ uint32_t hmul2(uint32_t a, uint32_t b) { uint32_t r; asm("mul.rn.bf16x2 %0, %1, %2;" : "=r"(r) : "r"(a), "r"(b)); return r; }
__device__ __forceinline__ uint32_t hfma2(uint32_t a, uint32_t b, uint32_t c) { uint32_t r; asm("fma.rn.bf16x2 %0, %1, %2, %3;" : "=r"(r) : "r"(a), "r"(b), "r"(c)); return r; }
__device__ __forceinline__ float rbf(float x) { uint32_t r; asm("cvt.rn.bf16x2.f32 %0, %1, %2;" : "=r"(r) : "f"(x), "f"(0.0f)); return __uint_as_float(r); }
__device__ __forceinline__ void stmatrix4(uint32_t a, uint32_t r0, uint32_t r1, uint32_t r2, uint32_t r3) {
  asm volatile("stmatrix.sync.aligned.m8n8.x4.shared.b16 [%0], {%1,%2,%3,%4};" ::"r"(a), "r"(r0), "r"(r1), "r"(r2), "r"(r3) : "memory");
}
__device__ __forceinline__ void stmatrix2(uint32_t a, uint32_t r0, uint32_t r1) {
  asm volatile("stmatrix.sync.aligned.m8n8.x2.shared.b16 [%0], {%1,%2};" ::"r"(a), "r"(r0), "r"(r1) : "memory");
}
__device__ __forceinline__ uint32_t movm(uint32_t a) { uint32_t r; asm("movmatrix.sync.aligned.m8n8.trans.b16 %0, %1;" : "=r"(r) : "r"(a)); return r; }
template <bool ACC> __device__ __forceinline__ void mma16(float* d, uint32_t a0, uint32_t a1, uint32_t a2, uint32_t a3, uint32_t b0, uint32_t b1) {
  if (ACC) asm("mma.sync.aligned.m16n8k16.row.col.f32.bf16.bf16.f32 {%0,%1,%2,%3}, {%4,%5,%6,%7}, {%8,%9}, {%0,%1,%2,%3};"
               : "+f"(d[0]), "+f"(d[1]), "+f"(d[2]), "+f"(d[3]) : "r"(a0), "r"(a1), "r"(a2), "r"(a3), "r"(b0), "r"(b1));
  else asm("mma.sync.aligned.m16n8k16.row.col.f32.bf16.bf16.f32 {%0,%1,%2,%3}, {%4,%5,%6,%7}, {%8,%9}, {%10,%10,%10,%10};"
           : "=f"(d[0]), "=f"(d[1]), "=f"(d[2]), "=f"(d[3]) : "r"(a0), "r"(a1), "r"(a2), "r"(a3), "r"(b0), "r"(b1), "f"(0.f));
}
__device__ __forceinline__ uint32_t pin(uint32_t v) { uint32_t r; asm volatile("shfl.sync.bfly.b32 %0, %1, 0, 31, 0xffffffff;" : "=r"(r) : "r"(v)); return r; }
template <class T> __device__ __forceinline__ T* pin(T* p) {
  const uint64_t a = reinterpret_cast<uint64_t>(p);
  return reinterpret_cast<T*>((uint64_t)pin((uint32_t)a) | ((uint64_t)pin((uint32_t)(a >> 32)) << 32));
}
__device__ __forceinline__ uint32_t upin(uint32_t v) { return __shfl_sync(0xffffffffu, v, 0); }
template <class T> __device__ __forceinline__ T* upin(T* p) {
  const uint64_t a = reinterpret_cast<uint64_t>(p);
  return reinterpret_cast<T*>((uint64_t)upin((uint32_t)a) | ((uint64_t)upin((uint32_t)(a >> 32)) << 32));
}
__device__ __forceinline__ int lane_id() { int v; asm volatile("mov.u32 %0, %%laneid;" : "=r"(v)); return v; }
__device__ __forceinline__ bool elect() {
  uint32_t p;
  asm volatile("{\n.reg .pred P;\nelect.sync _|P, 0xffffffff;\nselp.u32 %0, 1, 0, P;\n}" : "=r"(p));
  return p;
}
__device__ __forceinline__ uint32_t set_tag(uint32_t w, uint32_t tag) { uint32_t r; asm("lop3.b32 %0, %1, 0xfffffffe, %2, 0xea;" : "=r"(r) : "r"(w), "r"(tag)); return r; }
__device__ __forceinline__ uint32_t bitsel(uint32_t w, uint32_t m, uint32_t o) { uint32_t r; asm("lop3.b32 %0, %1, %2, %3, 0xe2;" : "=r"(r) : "r"(w), "r"(m), "r"(o)); return r; }
__device__ __forceinline__ uint32_t or3(uint32_t a, uint32_t b, uint32_t c) { uint32_t r; asm("lop3.b32 %0, %1, %2, %3, 0xfe;" : "=r"(r) : "r"(a), "r"(b), "r"(c)); return r; }
__device__ __forceinline__ uint32_t diff2(uint32_t a, uint32_t b, uint32_t tag) { uint32_t r; asm("lop3.b32 %0, %1, %2, %3, 0x7e;" : "=r"(r) : "r"(a), "r"(b), "r"(tag)); return r; }
__device__ __forceinline__ float2 cmul(float2 a, float2 b) { return make_float2(a.x * b.x - a.y * b.y, a.x * b.y + a.y * b.x); }

template<int TB> __device__ __forceinline__ void wgmma_ss_160_0(float (&d)[96], uint32_t al, uint32_t ah, uint32_t bl, uint32_t bh) {
  asm volatile("{\n.reg .b64 da, db;\nmov.b64 da, {%80, %81};\nmov.b64 db, {%82, %83};\n"
    "wgmma.mma_async.sync.aligned.m64n160k16.f32.bf16.bf16 {%0,%1,%2,%3,%4,%5,%6,%7,%8,%9,%10,%11,%12,%13,%14,%15,%16,%17,%18,%19,%20,%21,%22,%23,%24,%25,%26,%27,%28,%29,%30,%31,%32,%33,%34,%35,%36,%37,%38,%39,%40,%41,%42,%43,%44,%45,%46,%47,%48,%49,%50,%51,%52,%53,%54,%55,%56,%57,%58,%59,%60,%61,%62,%63,%64,%65,%66,%67,%68,%69,%70,%71,%72,%73,%74,%75,%76,%77,%78,%79}, da, db, 1, 1, 1, 1, %84;\n}\n"
    : "+f"(d[0]),"+f"(d[1]),"+f"(d[2]),"+f"(d[3]),"+f"(d[4]),"+f"(d[5]),"+f"(d[6]),"+f"(d[7]),"+f"(d[8]),"+f"(d[9]),"+f"(d[10]),"+f"(d[11]),"+f"(d[12]),"+f"(d[13]),"+f"(d[14]),"+f"(d[15]),"+f"(d[16]),"+f"(d[17]),"+f"(d[18]),"+f"(d[19]),"+f"(d[20]),"+f"(d[21]),"+f"(d[22]),"+f"(d[23]),"+f"(d[24]),"+f"(d[25]),"+f"(d[26]),"+f"(d[27]),"+f"(d[28]),"+f"(d[29]),"+f"(d[30]),"+f"(d[31]),"+f"(d[32]),"+f"(d[33]),"+f"(d[34]),"+f"(d[35]),"+f"(d[36]),"+f"(d[37]),"+f"(d[38]),"+f"(d[39]),"+f"(d[40]),"+f"(d[41]),"+f"(d[42]),"+f"(d[43]),"+f"(d[44]),"+f"(d[45]),"+f"(d[46]),"+f"(d[47]),"+f"(d[48]),"+f"(d[49]),"+f"(d[50]),"+f"(d[51]),"+f"(d[52]),"+f"(d[53]),"+f"(d[54]),"+f"(d[55]),"+f"(d[56]),"+f"(d[57]),"+f"(d[58]),"+f"(d[59]),"+f"(d[60]),"+f"(d[61]),"+f"(d[62]),"+f"(d[63]),"+f"(d[64]),"+f"(d[65]),"+f"(d[66]),"+f"(d[67]),"+f"(d[68]),"+f"(d[69]),"+f"(d[70]),"+f"(d[71]),"+f"(d[72]),"+f"(d[73]),"+f"(d[74]),"+f"(d[75]),"+f"(d[76]),"+f"(d[77]),"+f"(d[78]),"+f"(d[79])
    : "r"(al), "r"(ah), "r"(bl), "r"(bh), "n"(TB));
}
template<int TB> __device__ __forceinline__ void wgmma_ss_144_0(float (&d)[96], uint32_t al, uint32_t ah, uint32_t bl, uint32_t bh) {
  asm volatile("{\n.reg .b64 da, db;\nmov.b64 da, {%72, %73};\nmov.b64 db, {%74, %75};\n"
    "wgmma.mma_async.sync.aligned.m64n144k16.f32.bf16.bf16 {%0,%1,%2,%3,%4,%5,%6,%7,%8,%9,%10,%11,%12,%13,%14,%15,%16,%17,%18,%19,%20,%21,%22,%23,%24,%25,%26,%27,%28,%29,%30,%31,%32,%33,%34,%35,%36,%37,%38,%39,%40,%41,%42,%43,%44,%45,%46,%47,%48,%49,%50,%51,%52,%53,%54,%55,%56,%57,%58,%59,%60,%61,%62,%63,%64,%65,%66,%67,%68,%69,%70,%71}, da, db, 1, 1, 1, 1, %76;\n}\n"
    : "+f"(d[0]),"+f"(d[1]),"+f"(d[2]),"+f"(d[3]),"+f"(d[4]),"+f"(d[5]),"+f"(d[6]),"+f"(d[7]),"+f"(d[8]),"+f"(d[9]),"+f"(d[10]),"+f"(d[11]),"+f"(d[12]),"+f"(d[13]),"+f"(d[14]),"+f"(d[15]),"+f"(d[16]),"+f"(d[17]),"+f"(d[18]),"+f"(d[19]),"+f"(d[20]),"+f"(d[21]),"+f"(d[22]),"+f"(d[23]),"+f"(d[24]),"+f"(d[25]),"+f"(d[26]),"+f"(d[27]),"+f"(d[28]),"+f"(d[29]),"+f"(d[30]),"+f"(d[31]),"+f"(d[32]),"+f"(d[33]),"+f"(d[34]),"+f"(d[35]),"+f"(d[36]),"+f"(d[37]),"+f"(d[38]),"+f"(d[39]),"+f"(d[40]),"+f"(d[41]),"+f"(d[42]),"+f"(d[43]),"+f"(d[44]),"+f"(d[45]),"+f"(d[46]),"+f"(d[47]),"+f"(d[48]),"+f"(d[49]),"+f"(d[50]),"+f"(d[51]),"+f"(d[52]),"+f"(d[53]),"+f"(d[54]),"+f"(d[55]),"+f"(d[56]),"+f"(d[57]),"+f"(d[58]),"+f"(d[59]),"+f"(d[60]),"+f"(d[61]),"+f"(d[62]),"+f"(d[63]),"+f"(d[64]),"+f"(d[65]),"+f"(d[66]),"+f"(d[67]),"+f"(d[68]),"+f"(d[69]),"+f"(d[70]),"+f"(d[71])
    : "r"(al), "r"(ah), "r"(bl), "r"(bh), "n"(TB));
}
template<int TB> __device__ __forceinline__ void wgmma_ss_96_0(float (&d)[96], uint32_t al, uint32_t ah, uint32_t bl, uint32_t bh) {
  asm volatile("{\n.reg .b64 da, db;\nmov.b64 da, {%48, %49};\nmov.b64 db, {%50, %51};\n"
    "wgmma.mma_async.sync.aligned.m64n96k16.f32.bf16.bf16 {%0,%1,%2,%3,%4,%5,%6,%7,%8,%9,%10,%11,%12,%13,%14,%15,%16,%17,%18,%19,%20,%21,%22,%23,%24,%25,%26,%27,%28,%29,%30,%31,%32,%33,%34,%35,%36,%37,%38,%39,%40,%41,%42,%43,%44,%45,%46,%47}, da, db, 1, 1, 1, 1, %52;\n}\n"
    : "+f"(d[0]),"+f"(d[1]),"+f"(d[2]),"+f"(d[3]),"+f"(d[4]),"+f"(d[5]),"+f"(d[6]),"+f"(d[7]),"+f"(d[8]),"+f"(d[9]),"+f"(d[10]),"+f"(d[11]),"+f"(d[12]),"+f"(d[13]),"+f"(d[14]),"+f"(d[15]),"+f"(d[16]),"+f"(d[17]),"+f"(d[18]),"+f"(d[19]),"+f"(d[20]),"+f"(d[21]),"+f"(d[22]),"+f"(d[23]),"+f"(d[24]),"+f"(d[25]),"+f"(d[26]),"+f"(d[27]),"+f"(d[28]),"+f"(d[29]),"+f"(d[30]),"+f"(d[31]),"+f"(d[32]),"+f"(d[33]),"+f"(d[34]),"+f"(d[35]),"+f"(d[36]),"+f"(d[37]),"+f"(d[38]),"+f"(d[39]),"+f"(d[40]),"+f"(d[41]),"+f"(d[42]),"+f"(d[43]),"+f"(d[44]),"+f"(d[45]),"+f"(d[46]),"+f"(d[47])
    : "r"(al), "r"(ah), "r"(bl), "r"(bh), "n"(TB));
}
template<int TB> __device__ __forceinline__ void wgmma_ss_96_48(float (&d)[96], uint32_t al, uint32_t ah, uint32_t bl, uint32_t bh) {
  asm volatile("{\n.reg .b64 da, db;\nmov.b64 da, {%48, %49};\nmov.b64 db, {%50, %51};\n"
    "wgmma.mma_async.sync.aligned.m64n96k16.f32.bf16.bf16 {%0,%1,%2,%3,%4,%5,%6,%7,%8,%9,%10,%11,%12,%13,%14,%15,%16,%17,%18,%19,%20,%21,%22,%23,%24,%25,%26,%27,%28,%29,%30,%31,%32,%33,%34,%35,%36,%37,%38,%39,%40,%41,%42,%43,%44,%45,%46,%47}, da, db, 1, 1, 1, 1, %52;\n}\n"
    : "+f"(d[48]),"+f"(d[49]),"+f"(d[50]),"+f"(d[51]),"+f"(d[52]),"+f"(d[53]),"+f"(d[54]),"+f"(d[55]),"+f"(d[56]),"+f"(d[57]),"+f"(d[58]),"+f"(d[59]),"+f"(d[60]),"+f"(d[61]),"+f"(d[62]),"+f"(d[63]),"+f"(d[64]),"+f"(d[65]),"+f"(d[66]),"+f"(d[67]),"+f"(d[68]),"+f"(d[69]),"+f"(d[70]),"+f"(d[71]),"+f"(d[72]),"+f"(d[73]),"+f"(d[74]),"+f"(d[75]),"+f"(d[76]),"+f"(d[77]),"+f"(d[78]),"+f"(d[79]),"+f"(d[80]),"+f"(d[81]),"+f"(d[82]),"+f"(d[83]),"+f"(d[84]),"+f"(d[85]),"+f"(d[86]),"+f"(d[87]),"+f"(d[88]),"+f"(d[89]),"+f"(d[90]),"+f"(d[91]),"+f"(d[92]),"+f"(d[93]),"+f"(d[94]),"+f"(d[95])
    : "r"(al), "r"(ah), "r"(bl), "r"(bh), "n"(TB));
}
__device__ __forceinline__ void wgmma_init_160_0(float (&d)[96], uint32_t a0, uint32_t a1, uint32_t a2, uint32_t a3, uint32_t bl) {
  asm volatile("{\n.reg .b64 db;\nmov.b64 db, {%84, 0};\n"
    "wgmma.mma_async.sync.aligned.m64n160k16.f32.bf16.bf16 {%0,%1,%2,%3,%4,%5,%6,%7,%8,%9,%10,%11,%12,%13,%14,%15,%16,%17,%18,%19,%20,%21,%22,%23,%24,%25,%26,%27,%28,%29,%30,%31,%32,%33,%34,%35,%36,%37,%38,%39,%40,%41,%42,%43,%44,%45,%46,%47,%48,%49,%50,%51,%52,%53,%54,%55,%56,%57,%58,%59,%60,%61,%62,%63,%64,%65,%66,%67,%68,%69,%70,%71,%72,%73,%74,%75,%76,%77,%78,%79}, {%80,%81,%82,%83}, db, 0, 1, 1, 1;\n}\n"
    : "=f"(d[0]),"=f"(d[1]),"=f"(d[2]),"=f"(d[3]),"=f"(d[4]),"=f"(d[5]),"=f"(d[6]),"=f"(d[7]),"=f"(d[8]),"=f"(d[9]),"=f"(d[10]),"=f"(d[11]),"=f"(d[12]),"=f"(d[13]),"=f"(d[14]),"=f"(d[15]),"=f"(d[16]),"=f"(d[17]),"=f"(d[18]),"=f"(d[19]),"=f"(d[20]),"=f"(d[21]),"=f"(d[22]),"=f"(d[23]),"=f"(d[24]),"=f"(d[25]),"=f"(d[26]),"=f"(d[27]),"=f"(d[28]),"=f"(d[29]),"=f"(d[30]),"=f"(d[31]),"=f"(d[32]),"=f"(d[33]),"=f"(d[34]),"=f"(d[35]),"=f"(d[36]),"=f"(d[37]),"=f"(d[38]),"=f"(d[39]),"=f"(d[40]),"=f"(d[41]),"=f"(d[42]),"=f"(d[43]),"=f"(d[44]),"=f"(d[45]),"=f"(d[46]),"=f"(d[47]),"=f"(d[48]),"=f"(d[49]),"=f"(d[50]),"=f"(d[51]),"=f"(d[52]),"=f"(d[53]),"=f"(d[54]),"=f"(d[55]),"=f"(d[56]),"=f"(d[57]),"=f"(d[58]),"=f"(d[59]),"=f"(d[60]),"=f"(d[61]),"=f"(d[62]),"=f"(d[63]),"=f"(d[64]),"=f"(d[65]),"=f"(d[66]),"=f"(d[67]),"=f"(d[68]),"=f"(d[69]),"=f"(d[70]),"=f"(d[71]),"=f"(d[72]),"=f"(d[73]),"=f"(d[74]),"=f"(d[75]),"=f"(d[76]),"=f"(d[77]),"=f"(d[78]),"=f"(d[79])
    : "r"(a0), "r"(a1), "r"(a2), "r"(a3), "r"(bl));
}
__device__ __forceinline__ void wgmma_init_144_0(float (&d)[96], uint32_t a0, uint32_t a1, uint32_t a2, uint32_t a3, uint32_t bl) {
  asm volatile("{\n.reg .b64 db;\nmov.b64 db, {%76, 0};\n"
    "wgmma.mma_async.sync.aligned.m64n144k16.f32.bf16.bf16 {%0,%1,%2,%3,%4,%5,%6,%7,%8,%9,%10,%11,%12,%13,%14,%15,%16,%17,%18,%19,%20,%21,%22,%23,%24,%25,%26,%27,%28,%29,%30,%31,%32,%33,%34,%35,%36,%37,%38,%39,%40,%41,%42,%43,%44,%45,%46,%47,%48,%49,%50,%51,%52,%53,%54,%55,%56,%57,%58,%59,%60,%61,%62,%63,%64,%65,%66,%67,%68,%69,%70,%71}, {%72,%73,%74,%75}, db, 0, 1, 1, 1;\n}\n"
    : "=f"(d[0]),"=f"(d[1]),"=f"(d[2]),"=f"(d[3]),"=f"(d[4]),"=f"(d[5]),"=f"(d[6]),"=f"(d[7]),"=f"(d[8]),"=f"(d[9]),"=f"(d[10]),"=f"(d[11]),"=f"(d[12]),"=f"(d[13]),"=f"(d[14]),"=f"(d[15]),"=f"(d[16]),"=f"(d[17]),"=f"(d[18]),"=f"(d[19]),"=f"(d[20]),"=f"(d[21]),"=f"(d[22]),"=f"(d[23]),"=f"(d[24]),"=f"(d[25]),"=f"(d[26]),"=f"(d[27]),"=f"(d[28]),"=f"(d[29]),"=f"(d[30]),"=f"(d[31]),"=f"(d[32]),"=f"(d[33]),"=f"(d[34]),"=f"(d[35]),"=f"(d[36]),"=f"(d[37]),"=f"(d[38]),"=f"(d[39]),"=f"(d[40]),"=f"(d[41]),"=f"(d[42]),"=f"(d[43]),"=f"(d[44]),"=f"(d[45]),"=f"(d[46]),"=f"(d[47]),"=f"(d[48]),"=f"(d[49]),"=f"(d[50]),"=f"(d[51]),"=f"(d[52]),"=f"(d[53]),"=f"(d[54]),"=f"(d[55]),"=f"(d[56]),"=f"(d[57]),"=f"(d[58]),"=f"(d[59]),"=f"(d[60]),"=f"(d[61]),"=f"(d[62]),"=f"(d[63]),"=f"(d[64]),"=f"(d[65]),"=f"(d[66]),"=f"(d[67]),"=f"(d[68]),"=f"(d[69]),"=f"(d[70]),"=f"(d[71])
    : "r"(a0), "r"(a1), "r"(a2), "r"(a3), "r"(bl));
}
__device__ __forceinline__ void wgmma_init_96_0(float (&d)[96], uint32_t a0, uint32_t a1, uint32_t a2, uint32_t a3, uint32_t bl) {
  asm volatile("{\n.reg .b64 db;\nmov.b64 db, {%52, 0};\n"
    "wgmma.mma_async.sync.aligned.m64n96k16.f32.bf16.bf16 {%0,%1,%2,%3,%4,%5,%6,%7,%8,%9,%10,%11,%12,%13,%14,%15,%16,%17,%18,%19,%20,%21,%22,%23,%24,%25,%26,%27,%28,%29,%30,%31,%32,%33,%34,%35,%36,%37,%38,%39,%40,%41,%42,%43,%44,%45,%46,%47}, {%48,%49,%50,%51}, db, 0, 1, 1, 1;\n}\n"
    : "=f"(d[0]),"=f"(d[1]),"=f"(d[2]),"=f"(d[3]),"=f"(d[4]),"=f"(d[5]),"=f"(d[6]),"=f"(d[7]),"=f"(d[8]),"=f"(d[9]),"=f"(d[10]),"=f"(d[11]),"=f"(d[12]),"=f"(d[13]),"=f"(d[14]),"=f"(d[15]),"=f"(d[16]),"=f"(d[17]),"=f"(d[18]),"=f"(d[19]),"=f"(d[20]),"=f"(d[21]),"=f"(d[22]),"=f"(d[23]),"=f"(d[24]),"=f"(d[25]),"=f"(d[26]),"=f"(d[27]),"=f"(d[28]),"=f"(d[29]),"=f"(d[30]),"=f"(d[31]),"=f"(d[32]),"=f"(d[33]),"=f"(d[34]),"=f"(d[35]),"=f"(d[36]),"=f"(d[37]),"=f"(d[38]),"=f"(d[39]),"=f"(d[40]),"=f"(d[41]),"=f"(d[42]),"=f"(d[43]),"=f"(d[44]),"=f"(d[45]),"=f"(d[46]),"=f"(d[47])
    : "r"(a0), "r"(a1), "r"(a2), "r"(a3), "r"(bl));
}
__device__ __forceinline__ void wgmma_init_96_48(float (&d)[96], uint32_t a0, uint32_t a1, uint32_t a2, uint32_t a3, uint32_t bl) {
  asm volatile("{\n.reg .b64 db;\nmov.b64 db, {%52, 0};\n"
    "wgmma.mma_async.sync.aligned.m64n96k16.f32.bf16.bf16 {%0,%1,%2,%3,%4,%5,%6,%7,%8,%9,%10,%11,%12,%13,%14,%15,%16,%17,%18,%19,%20,%21,%22,%23,%24,%25,%26,%27,%28,%29,%30,%31,%32,%33,%34,%35,%36,%37,%38,%39,%40,%41,%42,%43,%44,%45,%46,%47}, {%48,%49,%50,%51}, db, 0, 1, 1, 1;\n}\n"
    : "=f"(d[48]),"=f"(d[49]),"=f"(d[50]),"=f"(d[51]),"=f"(d[52]),"=f"(d[53]),"=f"(d[54]),"=f"(d[55]),"=f"(d[56]),"=f"(d[57]),"=f"(d[58]),"=f"(d[59]),"=f"(d[60]),"=f"(d[61]),"=f"(d[62]),"=f"(d[63]),"=f"(d[64]),"=f"(d[65]),"=f"(d[66]),"=f"(d[67]),"=f"(d[68]),"=f"(d[69]),"=f"(d[70]),"=f"(d[71]),"=f"(d[72]),"=f"(d[73]),"=f"(d[74]),"=f"(d[75]),"=f"(d[76]),"=f"(d[77]),"=f"(d[78]),"=f"(d[79]),"=f"(d[80]),"=f"(d[81]),"=f"(d[82]),"=f"(d[83]),"=f"(d[84]),"=f"(d[85]),"=f"(d[86]),"=f"(d[87]),"=f"(d[88]),"=f"(d[89]),"=f"(d[90]),"=f"(d[91]),"=f"(d[92]),"=f"(d[93]),"=f"(d[94]),"=f"(d[95])
    : "r"(a0), "r"(a1), "r"(a2), "r"(a3), "r"(bl));
}
__device__ __forceinline__ void wgmma_rs_72(float (&d)[36], uint32_t a0, uint32_t a1, uint32_t a2, uint32_t a3, uint32_t bl, uint32_t bh, int sd) {
  asm volatile("{\n.reg .pred p;\n.reg .b64 db;\nsetp.ne.b32 p, %42, 0;\nmov.b64 db, {%40, %41};\n"
    "wgmma.mma_async.sync.aligned.m64n72k16.f32.bf16.bf16 {%0,%1,%2,%3,%4,%5,%6,%7,%8,%9,%10,%11,%12,%13,%14,%15,%16,%17,%18,%19,%20,%21,%22,%23,%24,%25,%26,%27,%28,%29,%30,%31,%32,%33,%34,%35}, {%36,%37,%38,%39}, db, p, 1, 1, 1;\n}\n"
    : "+f"(d[0]),"+f"(d[1]),"+f"(d[2]),"+f"(d[3]),"+f"(d[4]),"+f"(d[5]),"+f"(d[6]),"+f"(d[7]),"+f"(d[8]),"+f"(d[9]),"+f"(d[10]),"+f"(d[11]),"+f"(d[12]),"+f"(d[13]),"+f"(d[14]),"+f"(d[15]),"+f"(d[16]),"+f"(d[17]),"+f"(d[18]),"+f"(d[19]),"+f"(d[20]),"+f"(d[21]),"+f"(d[22]),"+f"(d[23]),"+f"(d[24]),"+f"(d[25]),"+f"(d[26]),"+f"(d[27]),"+f"(d[28]),"+f"(d[29]),"+f"(d[30]),"+f"(d[31]),"+f"(d[32]),"+f"(d[33]),"+f"(d[34]),"+f"(d[35])
    : "r"(a0), "r"(a1), "r"(a2), "r"(a3), "r"(bl), "r"(bh), "r"(sd));
}
__device__ __forceinline__ void wgmma_rs_48(float (&d)[24], uint32_t a0, uint32_t a1, uint32_t a2, uint32_t a3, uint32_t bl, uint32_t bh, int sd) {
  asm volatile("{\n.reg .pred p;\n.reg .b64 db;\nsetp.ne.b32 p, %30, 0;\nmov.b64 db, {%28, %29};\n"
    "wgmma.mma_async.sync.aligned.m64n48k16.f32.bf16.bf16 {%0,%1,%2,%3,%4,%5,%6,%7,%8,%9,%10,%11,%12,%13,%14,%15,%16,%17,%18,%19,%20,%21,%22,%23}, {%24,%25,%26,%27}, db, p, 1, 1, 1;\n}\n"
    : "+f"(d[0]),"+f"(d[1]),"+f"(d[2]),"+f"(d[3]),"+f"(d[4]),"+f"(d[5]),"+f"(d[6]),"+f"(d[7]),"+f"(d[8]),"+f"(d[9]),"+f"(d[10]),"+f"(d[11]),"+f"(d[12]),"+f"(d[13]),"+f"(d[14]),"+f"(d[15]),"+f"(d[16]),"+f"(d[17]),"+f"(d[18]),"+f"(d[19]),"+f"(d[20]),"+f"(d[21]),"+f"(d[22]),"+f"(d[23])
    : "r"(a0), "r"(a1), "r"(a2), "r"(a3), "r"(bl), "r"(bh), "r"(sd));
}
template<int N,int OFF,int TB> __device__ __forceinline__ void wgmma_ss(float (&d)[96], uint32_t al, uint32_t ah, uint32_t bl, uint32_t bh) {
  if constexpr (N==160 && OFF==0) wgmma_ss_160_0<TB>(d, al, ah, bl, bh);
  else if constexpr (N==144 && OFF==0) wgmma_ss_144_0<TB>(d, al, ah, bl, bh);
  else if constexpr (N==96 && OFF==0) wgmma_ss_96_0<TB>(d, al, ah, bl, bh);
  else if constexpr (N==96 && OFF==48) wgmma_ss_96_48<TB>(d, al, ah, bl, bh);
}

__device__ __forceinline__ void dft3(float2& a, float2& b, float2& c) {
  const float s = 0.86602540378443864676f;
  float2 t = make_float2(b.x + c.x, b.y + c.y), d = make_float2(b.x - c.x, b.y - c.y);
  float2 m = make_float2(fmaf(-0.5f, t.x, a.x), fmaf(-0.5f, t.y, a.y));
  a = make_float2(a.x + t.x, a.y + t.y);
  b = make_float2(fmaf(s, d.y, m.x), fmaf(-s, d.x, m.y));
  c = make_float2(fmaf(-s, d.y, m.x), fmaf(s, d.x, m.y));
}
__device__ __forceinline__ void dft9(float2 (&x)[9]) {
  const float2 w1 = make_float2(0.76604444311897803520f, -0.64278760968653932632f);
  const float2 w2 = make_float2(0.17364817766693034885f, -0.98480775301220805937f);
  const float2 w4 = make_float2(-0.93969262078590838405f, -0.34202014332566873304f);
  dft3(x[0], x[3], x[6]); dft3(x[1], x[4], x[7]); dft3(x[2], x[5], x[8]);
  x[4] = cmul(x[4], w1); x[7] = cmul(x[7], w2); x[5] = cmul(x[5], w2); x[8] = cmul(x[8], w4);
  dft3(x[0], x[1], x[2]); dft3(x[3], x[4], x[5]); dft3(x[6], x[7], x[8]);
  float2 t;
  t = x[1]; x[1] = x[3]; x[3] = t;
  t = x[2]; x[2] = x[6]; x[6] = t;
  t = x[5]; x[5] = x[7]; x[7] = t;
}

__device__ __forceinline__ uint32_t* mod_ptr(Scratch* sc, int u, int t128) {
  const int i = t128 & 15;
  return u < 72 ? sc->moda + (t128 >> 4) * (2 * D_) + 16 * u + 2 * (i & 7) + (i >> 3) : sc->mod + 16 * (u - 72) + i;
}
__device__ __forceinline__ void mod_unit(Scratch* sc, int u, int t128, uint32_t sw_, uint32_t bar, int ph, uint32_t rb, uint32_t tag) {
  const int w = t128 >> 5, l = t128 & 31;
  uint32_t b[18];
#pragma unroll
  for (int i = 0; i < 18; i++) b[i] = lds(red + 512 + (72 * w + 4 * i + (l & 3)) * 4);
  const uint32_t sa = pin(sw_ + (144 * w + (l & 7) + 8 * (l >> 4)) * 32 + (((l >> 3) ^ (l >> 2)) & 1) * 16);
  const uint32_t sr = pin(rb + (l >> 2) * 16 + w * 4);
  uint32_t* const dst = pin(mod_ptr(sc, u, t128));
  const int kind = u / 36;
  const float mul = __uint_as_float(pin(__float_as_uint(kind == 0 ? 16.0f : 1.0f))), add = __uint_as_float(pin(__float_as_uint(kind == 1 || kind == 4 ? 1.0f : 0.0f)));
  mbar_wait(bar, ph);
  float d[3][4];
#pragma unroll
  for (int i = 0; i < 9; i++) {
    uint32_t a0, a1, a2, a3;
    asm volatile("ldmatrix.sync.aligned.m8n8.x4.trans.shared.b16 {%0,%1,%2,%3}, [%4];" : "=r"(a0), "=r"(a1), "=r"(a2), "=r"(a3) : "r"(sa + i * 512) : "memory");
    if (i < 3) mma16<false>(d[i], a0, a1, a2, a3, b[2 * i], b[2 * i + 1]);
    else mma16<true>(d[i % 3], a0, a1, a2, a3, b[2 * i], b[2 * i + 1]);
  }
  if ((l & 3) == 0) { sts(sr, __float_as_uint(d[0][0] + d[1][0] + d[2][0])); sts(sr + 128, __float_as_uint(d[0][2] + d[1][2] + d[2][2])); }
  bar_sync(4, 128);
  const uint4 v = lds4(rb + (l & 15) * 16);
  const float m = rbf(fmaf(rbf((__uint_as_float(v.x) + __uint_as_float(v.y)) + (__uint_as_float(v.z) + __uint_as_float(v.w))), mul, add));
  if (u < 72 || t128 < 16) *dst = __float_as_uint(m) | tag;
}

__device__ __forceinline__ float rsq(float x) { float r; asm("rsqrt.approx.ftz.f32 %0, %1;" : "=f"(r) : "f"(x)); return r; }
__device__ __forceinline__ void ln_stats2(const float (&a)[18], const float (&b)[18], float sc, float& oa, float& ra, float& ob, float& rb) {
  float v[4] = {0.f, 0.f, 0.f, 0.f}, w[4] = {0.f, 0.f, 0.f, 0.f};
#pragma unroll
  for (int i = 0; i < 18; i += 2) {
    v[0] += a[i]; v[1] = fmaf(a[i], a[i], v[1]); v[2] += b[i]; v[3] = fmaf(b[i], b[i], v[3]);
    w[0] += a[i + 1]; w[1] = fmaf(a[i + 1], a[i + 1], w[1]); w[2] += b[i + 1]; w[3] = fmaf(b[i + 1], b[i + 1], w[3]);
  }
#pragma unroll
  for (int e = 0; e < 4; e++) v[e] += w[e];
#pragma unroll
  for (int o = 16; o; o >>= 1) {
#pragma unroll
    for (int e = 0; e < 4; e++) v[e] += __shfl_xor_sync(0xffffffffu, v[e], o);
  }
  const float ma = v[0] * (1.0f / D_), mb = v[2] * (1.0f / D_);
  ra = sc * rsq(fmaxf(fmaf(-ma, ma, v[1] * (1.0f / D_)), 0.f) + 1e-5f);
  rb = sc * rsq(fmaxf(fmaf(-mb, mb, v[3] * (1.0f / D_)), 0.f) + 1e-5f);
  oa = -ma * ra; ob = -mb * rb;
}

__device__ __forceinline__ void ln_stats1(const float (&a)[18], float sc, float& oa, float& ra) {
  float v[3] = {a[0], a[1], a[2]}, w[3] = {a[0] * a[0], a[1] * a[1], a[2] * a[2]};
#pragma unroll
  for (int i = 3; i < 18; i++) { v[i % 3] += a[i]; w[i % 3] = fmaf(a[i], a[i], w[i % 3]); }
  float s = v[0] + v[1] + v[2], q = w[0] + w[1] + w[2];
#pragma unroll
  for (int o = 16; o; o >>= 1) { s += __shfl_xor_sync(0xffffffffu, s, o); q += __shfl_xor_sync(0xffffffffu, q, o); }
  const float m = s * (1.0f / D_);
  ra = sc * rsq(fmaxf(fmaf(-m, m, q * (1.0f / D_)), 0.f) + 1e-5f);
  oa = -m * ra;
}

__device__ __forceinline__ float tmat(int c, int q, int j) {
  const int ph = q == 1 ? 1024 * j : (q >> 1) * (c + 128 * j) + 512 * (q & 1);
  return __cosf((float)(((ph + 1024) & 2047) - 1024) * (6.283185307179586f / 2048.0f));
}
__device__ __forceinline__ uint32_t line_off(int k1, int kap, int pi, int f) {
  int kd = 64 * k1 + 9 * kap;
  if (kap == 0 && k1 > 4) kd -= 288;
  if (kd >= D_) kd -= D_;
  return pi * 2400 + ((min(kd, D_ - kd) ^ f) << 3);
}

struct Ring { uint32_t st, ph; };
template <bool G2, class T> __device__ __forceinline__ void ring_next(T& st, T& ph) {
  if (++st == NST) st = 0;
  ph ^= ((G2 ? 0xDu : 0x1u) >> st) & 1;
}
__device__ __forceinline__ void arrive_if(uint32_t a, uint32_t p) {
  asm volatile("{\n.reg .pred p;\nsetp.ne.u32 p, %1, 0;\n@p mbarrier.arrive.shared::cta.b64 _, [%0];\n}" ::"r"(a), "r"(p) : "memory");
}
template <int NA> __device__ __forceinline__ void reg_fence_n(float (&d)[96]) {
#pragma unroll
  for (int i = 0; i < NA; i++) asm volatile("" : "+f"(d[i])::"memory");
}
template <int MODE, class F>
__device__ __forceinline__ void gemm_main(float (&acc)[96], uint32_t da0, uint32_t da1, uint32_t db0, int wg, Ring& rg,
                                          int J, const uint32_t (&bias)[4], F&& side_work) {
  constexpr int NKB = MODE == 3 ? 36 : 32;
  constexpr uint32_t HA = 0x40000040u, HB = MODE == 3 ? 0xC0000010u : 0x80000020u;
  constexpr uint32_t KA = 2048 >> 4, KB = (MODE == 3 ? 512 : 1024) >> 4;
  constexpr int NA = MODE == 3 ? 72 : MODE == 1 ? 96 : 80;
  const uint32_t t = threadIdx.x & 127;
  const uint32_t eb = full0 + 8 * NST;
  constexpr uint32_t SP = (MODE == 3 ? STAGE2 : STAGE) >> 4;
  uint32_t pb = 0, prel = 0, ok = 0, sn = rg.st * SP;
  int n = MODE != 3 ? X1K + 2 * wg : wg ? NKB - J : NKB, nh = 0, ng = MODE == 3 && !wg;
  {
    constexpr uint32_t dh = (sbase + O_HALF) >> 4;
    const bool t0 = (t & 3) == 0;
    const uint32_t b0 = t0 ? bias[0] : 0, b1 = t0 ? bias[1] : 0, b2 = t0 ? bias[2] : 0, b3 = t0 ? bias[3] : 0;
    wg_fence();
    if (MODE == 0) wgmma_init_160_0(acc, b0, b1, 0, 0, dh);
    else if (MODE == 3) wgmma_init_144_0(acc, b0, b1, b0, b1, dh);
    else { wgmma_init_96_0(acc, b0, b1, 0, 0, dh); wgmma_init_96_48(acc, b2, b3, 0, 0, dh); }
    wg_commit();
    wg_wait<0>();
    reg_fence_n<NA>(acc);
  }
#pragma unroll 1
  for (int pass = MODE == 3 ? 0 : -1;; pass++) {
#pragma unroll 1
    do {
      mbar_wait(full0 + 8 * rg.st, rg.ph);
#pragma unroll 1
      do {
      const uint32_t so = sn, cb = eb + 8 * rg.st;
      reg_fence_n<NA>(acc);
      if (MODE == 1 && wg) {
        wg_fence();
#pragma unroll
        for (int k = 0; k < 4; k++) wgmma_ss<96, 48, 1>(acc, da1 + so + k * KA, HA, db0 + so + k * KB, HB);
        wg_commit();
      }
      wg_fence();
#pragma unroll
      for (int k = 0; k < 4; k++) {
        if (k == 2) asm volatile("{\n.reg .pred p;\nsetp.eq.s32 p, %0, %1;\n@p bar.arrive 1, 256;\n}" ::"r"(n), "r"(ng) : "memory");
        if (k == 1 && MODE != 1) { wg_commit(); wg_wait<1>(); arrive_if(pb, prel); }
        if (k == 2) { ring_next<MODE == 3>(rg.st, rg.ph); sn = rg.st * SP; ok = mbar_test(full0 + 8 * rg.st, rg.ph); }
        if (MODE == 0) wgmma_ss<160, 0, 1>(acc, da0 + so + k * KA, HA, db0 + so + k * KB, HB);
        else if (MODE == 3) wgmma_ss<144, 0, 1>(acc, da0 + so + k * KA, HA, db0 + so + k * KB, HB);
        else wgmma_ss<96, 0, 1>(acc, da0 + so + k * KA, HA, db0 + so + k * KB, HB);
      }
      wg_commit();
      if (MODE == 1) { wg_wait<1>(); arrive_if(pb, prel); }
      reg_fence_n<NA>(acc);
      pb = cb; prel = t == 0 && (MODE != 0 || n != nh);
      } while (--n && ok);
    } while (n);
    if (pass == wg) break;
    if (MODE != 3 && pass < 0) {
      side_work();
      n = NKB - X1K - (J + 2) * wg;
      if (!wg) { ng = 1; if (J < NST) nh = NST; }
      continue;
    }
    wg_wait<0>();
    arrive_if(pb, prel);
    prel = 0;
    n = J;
    if (MODE == 0 && J < NST) bar_arrive(11, 256);
    bar_sync(1, 256);
  }
  if (MODE == 0 && J < NST && !wg) bar_sync(11, 256);
  wg_wait<0>();
  reg_fence_n<NA>(acc);
  if (MODE != 3) arrive_if(pb, prel);
}

constexpr float GK1 = 2.0f * 0.7978845608028654f, GK3 = 8.0f * 0.044715f * 0.7978845608028654f;

__device__ __forceinline__ int kb2_order(int i) { const int wv = i / 6; return 6 * (i - 6 * wv) + ((0x431250 >> (4 * wv)) & 7); }

__device__ __forceinline__ int kb2_pos(int kb) { const int hf = kb >= 36, k = kb - 36 * hf, gr = k / 6; return 64 * hf + gr + 6 * ((0x154230 >> (4 * (k - 6 * gr))) & 7); }

__device__ __forceinline__ void wait_flags(const unsigned* p, int idx, unsigned target, uint32_t& ready) {
  int it = 0;
  while (!((ready >> idx) & 1) && it++ < SPIN_MAX) ready = __ballot_sync(0xffffffffu, (int)(ld_rlx(p) - target) >= 0);
}

enum { B_FULL = 0, B_EMPTY = 6, B_S4 = 12, B_S5, B_LAND, B_FLT = B_LAND + 6, B_Z1, B_Z2, B_GO, B_X, B_WM, B_NUM, B_W0 = B_NUM };

__global__ void __launch_bounds__(NTHR, 1)
fused_kernel(const Params p, const __grid_constant__ Maps maps) {
  extern __shared__ __align__(1024) uint8_t smem_raw[];
  const int bx = blockIdx.x, cta = bx < 112 || bx >= 130 ? bx : bx < 114 ? bx + 16 : bx - 2;
  const int tid = threadIdx.x, t128 = tid & 127;
  const int wp = __shfl_sync(0xffffffffu, tid >> 5, 0), wg = wp >> 2;
  const int l = tid & 31, g = l >> 2, t = l & 3;
  Scratch* const sc = p.s;
  const bool rows = cta < 128;
  const int mu = rows ? cta + 4 : cta - 128;
  const int R = mu - 12;

  uint32_t xr[18];
  uint32_t cv[3];
  const unsigned ep0 = ld_rlx(&sc->cnt[C_EP + l]);
  if (wg == 2) {
#pragma unroll
    for (int i = 0; i < 3; i++) cv[i] = ld_nc(reinterpret_cast<const uint32_t*>(p.c) + min(t128 + 128 * i, 287));
    if (wp == 9 && l < 9 && rows) {
      const int h = 9 * cta + l;
      prefetch_l2(reinterpret_cast<const uint8_t*>(p.wmod) + (size_t)(h >> 1) * (12 * D_) + (h & 1) * (2 * D_), 2 * D_);
    }
    if (tid == 256 && mu < 72) {
      mbar_init(full0 + 8 * B_W0, 1);
      fence_async_smem();
      mbar_expect(full0 + 8 * B_W0, 18432);
#pragma unroll 1
      for (int i = 0; i < 3; i++) tma2d(sbase + O_P2 + i * 6144, &maps.wm, 16 * mu, 192 * i, full0 + 8 * B_W0);
    }
    __syncwarp();
#pragma unroll 1
    for (int u = mu < 72 ? mu : 72 + mu; u < 216; u += u < 72 ? 72 : NCTA) if (u < 72 || t128 < 16) *mod_ptr(sc, u, t128) = 0;
    if (wp == 11 && smem_u32(smem_raw) != sbase) __trap();
    if (wp >= 10 && elect()) {
#pragma unroll 1
      for (int i = wp - 10; i < B_NUM; i += 2) mbar_init(full0 + 8 * i, i == B_FLT ? 4 : i == B_WM ? 3 : i < B_S4 ? 2 : 1);
      fence_async_smem();
    }
    __syncwarp();
  } else if (rows) {
    const uint32_t* xs = reinterpret_cast<const uint32_t*>(p.x) + (size_t)(cta + 128 * ((wp & 3) + 8 * wg)) * 288 + l;
#pragma unroll
    for (int i = 0; i < 9; i++) { xr[i] = ld_nc(xs + 32 * i); xr[9 + i] = ld_nc(xs + 512 * 288 + 32 * i); }
  }
  if (tid == 64 && cta == NCTA - 1) prefetch_l2(p.tab, sizeof(T_TAB));
  __syncwarp();
  auto tag_of = [](unsigned e) { return (e & 0x7fffu) | 0x8000u; };
  const int kap = 8 * ((wp & 3) ^ (wg & 1)) + g;
  uint32_t tb[4], sb1[3], lo[9];
#pragma unroll
  for (int i = 0; i < 4; i++) tb[i] = pin(pack_bf16(tmat(cta, 8 * (i >> 1) + g, t + 8 * (i & 1)), tmat(cta, 8 * (i >> 1) + g, t + 8 * (i & 1) + 4)));
#pragma unroll
  for (int i = 0; i < 3; i++) {
    const int d = 48 * wp + 16 * i + (l & 15);
    sb1[i] = pin(sbase + O_B1 + (l >> 4) * 9216 + (d % 9) * 1024 + (d & 63) * 16);
  }
#pragma unroll
  for (int k1 = 0; k1 < 9; k1++) lo[k1] = pin(sbase + O_Z1 + line_off(k1, kap, 4 * wg + t, cta & 3));
  const uint32_t snt = pin(sbase + O_NRM + ((l & 7) + 8 * (l >> 4)) * 1168 + (48 * wp + (l & 8)) * 2), sn = pin(sbase + O_NRM + wp * 2336 + l * 4);
  const uint32_t smask = pin(t ? 0u : 0xffff0000u);
  const uint32_t* const mp = pin(sc->moda + (cta >> 4) * (2 * D_) + 48 * wp + 2 * g);
  const uint4* const ftab = pin(p.tab + TB_F + (t128 ^ (wg << 5)));

  if (wg == 2) {
#pragma unroll
    for (int i = 0; i < 3; i++) {
      const float c0 = bf_lo(cv[i]), c1 = bf_hi(cv[i]);
      sts(red + 512 + min(t128 + 128 * i, 287) * 4, pack_bf16(__fdividef(c0, 1.0f + __expf(-c0)), __fdividef(c1, 1.0f + __expf(-c1))));
    }
    if (wp == 10) sts(sbase + O_HALF + 4 * l, l < 4 ? 0x3f003f00u : 0u);
    if (t128 == 0) sts(full0 + 248, ep0 + 1);
    if (wp == 9 && l < 11) asm volatile("prefetch.tensormap [%0];" ::"l"(&maps.z1 + l) : "memory");
    bar_sync(4, 128);
    if (mu < 72) {
      mod_unit(sc, mu, t128, sbase + O_P2, full0 + 8 * B_W0, 0, red, tag_of(upin(ep0) + 1));
    }
  }
  const int pi = R / 15, col0 = 20 * (R - 15 * pi);
  const int xu = DF_ * pi + col0, xv = DF_ * (pi ? 16 - pi : 8) + col0;
  auto load_filter = [&](int a) {
    const int x = (a & 1) ? xv : xu;
    const bool wide = (x & 15) > 12;
    mbar_expect(full0 + 8 * B_FLT, wide ? 12288 : 8192);
    tma2d(sbase + O_RAW + a * 12288, &maps.wf[a & 2], x & ~15, 0, full0 + 8 * B_FLT);
    if (wide) tma2d(sbase + O_RAW + a * 12288 + 8192, &maps.wf[(a & 2) + 1], (x & ~15) + 32, 0, full0 + 8 * B_FLT);
  };
  uint4 af[4];
  if (rows) {
    uint2 ms[3], mc[3];
    auto load_mod = [&](uint32_t o = 0) {
#pragma unroll
      for (int i = 0; i < 3; i++) { ms[i] = ld_rlx2(mp + 2 * o + 16 * i); mc[i] = ld_rlx2(mp + 2 * o + D_ + 16 * i); }
    };
    if (wg < 2) {
      float a[18], b[18];
#pragma unroll
      for (int i = 0; i < 9; i++) { a[2 * i] = bf_lo(xr[i]); a[2 * i + 1] = bf_hi(xr[i]); b[2 * i] = bf_lo(xr[9 + i]); b[2 * i + 1] = bf_hi(xr[9 + i]); }
      float oa, ra, ob, rb;
      ln_stats2(a, b, 1.0f, oa, ra, ob, rb);
      load_mod((__float_as_uint(ra) | __float_as_uint(rb)) >> 31);
#pragma unroll
      for (int i = 0; i < 9; i++) {
        sts(sn + i * 128, pack_bf16(fmaf(a[2 * i], ra, oa), fmaf(a[2 * i + 1], ra, oa)));
        sts(sn + 1168 + i * 128, pack_bf16(fmaf(b[2 * i], rb, ob), fmaf(b[2 * i + 1], rb, ob)));
      }
      bar_arrive(10, NTHR);
#pragma unroll
      for (int kk = 0; kk < 4; kk++) af[kk] = ld_nc4(ftab + kk * 128);
      bar_sync(1, 256);
    } else {
      bar_sync(10, NTHR);
      load_mod();
      if (wp >= 10 && elect()) prefetch_l2(reinterpret_cast<const uint8_t*>(wp == 10 ? p.wr : p.wi) + cta * 9248, 9248);
      __syncwarp();
    }
    float rs[3][8];
#pragma unroll
    for (int i = 0; i < 3; i++) {
      uint32_t a0, a1, a2, a3;
      asm volatile("ldmatrix.sync.aligned.m8n8.x4.trans.shared.b16 {%0,%1,%2,%3}, [%4];" : "=r"(a0), "=r"(a1), "=r"(a2), "=r"(a3)
                   : "r"(snt + 32 * i) : "memory");
      mma16<false>(&rs[i][0], a0, a1, a2, a3, tb[0], tb[1]);
      mma16<false>(&rs[i][4], a0, a1, a2, a3, tb[2], tb[3]);
    }
    const uint32_t tag16 = tag_of(upin(ep0) + 1), tag1 = tag16 & 1;
    {
      int it = 0;
#pragma unroll 1
      while (true) {
        uint32_t bad = 0;
#pragma unroll
        for (int i = 0; i < 3; i++) bad |= diff2(ms[i].x, ms[i].y, tag16) | diff2(mc[i].x, mc[i].y, tag16);
        if (!any(bad & 0xffffu) || ++it > SPIN_MAX) break;
        load_mod();
      }
#pragma unroll
      for (int i = 0; i < 3; i++) {
        const float c0 = bf_hi(mc[i].x), c1 = bf_hi(mc[i].y);
        const float s0 = __uint_as_float(ms[i].x & smask), s1 = __uint_as_float(ms[i].y & smask);
        stmatrix4(sb1[i], pack_bf16(fmaf(rs[i][0], c0, s0), rs[i][1] * c0), pack_bf16(fmaf(rs[i][2], c1, s1), rs[i][3] * c1),
                  pack_bf16(rs[i][4] * c0, rs[i][5] * c0), pack_bf16(rs[i][6] * c1, rs[i][7] * c1));
      }
    }
    fence_async_smem();
    if (wg == 2) {
      bar_arrive(5, NTHR);
      if (R >= 0 && elect()) load_filter(wp - 8);
      __syncwarp();
      const int slot = 4 * (cta & 7) + ((cta >> 4) & 3) + 32 * (2 * (cta >> 6) + ((cta >> 3) & 1));
      const uint32_t c0 = upin(40 * slot), c1 = upin(60 * (wp & 1)), src = upin(sbase + O_Z1 + (wp & 1) * 9600);
      const CUtensorMap* mz = upin(&maps.z1);
      unsigned* hint = pin(sc->cnt + C_Z1 + 32 * (wp & 1));
      if (wp < 10) {
        bar_sync(2 + (wp & 1), 160);
        if (elect()) tma_st2d(mz, src, c0, c1);
        pause(HD1);
        if (elect()) red_add(hint, 1);
        bulk_commit_wait();
        __syncwarp();
      }
    } else {
      bar_sync(5, NTHR);
      float acc[36];
      const uint32_t db = (((sbase + O_B1 + wg * 9216) & 0x3FFFF) >> 4) | ((128 >> 4) << 16);
      wg_fence();
#pragma unroll
      for (int kk = 0; kk < 4; kk++) wgmma_rs_72(acc, af[kk].x, af[kk].y, af[kk].z, af[kk].w, db + kk * 16, 1024 >> 4, kk);
      wg_commit();
      wg_wait<0>();
      reg_fence(acc);
      float2 za[9], zb[9];
#pragma unroll
      for (int i = 0; i < 9; i++) { za[i] = make_float2(acc[4 * i], acc[4 * i + 2]); zb[i] = make_float2(acc[4 * i + 1], acc[4 * i + 3]); }
      dft9(za); dft9(zb);
      if ((wp & 3) == wg) {
        const float sp = g ? 0.f : 1.f;
#pragma unroll
        for (int k = 1; k < 5; k++) {
          float2 a = za[k], b = za[9 - k];
          za[k] = make_float2(fmaf(sp, b.x, a.x), fmaf(-sp, b.y, a.y)); za[9 - k] = make_float2(fmaf(-sp, a.x, b.x), fmaf(sp, a.y, b.y));
          a = zb[k]; b = zb[9 - k];
          zb[k] = make_float2(fmaf(sp, b.x, a.x), fmaf(-sp, b.y, a.y)); zb[9 - k] = make_float2(fmaf(-sp, a.x, b.x), fmaf(sp, a.y, b.y));
        }
        const uint32_t w0 = set_tag(pack_bf16(za[0].y, 0.f), tag1), w1 = pack_bf16(zb[0].y, 0.f);
        asm volatile("{\n.reg .pred p;\nsetp.eq.u32 p, %3, 0;\n@p st.shared.v2.b32 [%0], {%1,%2};\n}" ::"r"(lo[0] + 288 * 8), "r"(w0), "r"(w1), "r"(g) : "memory");
        za[0].y = g ? za[0].y : 0.f; zb[0].y = g ? zb[0].y : 0.f;
      }
#pragma unroll
      for (int k1 = 0; k1 < 9; k1++) sts2(lo[k1], set_tag(pack_bf16(za[k1].x, za[k1].y), tag1), pack_bf16(zb[k1].x, zb[k1].y));
      fence_async_smem();
      bar_arrive(2 + wg, 160);
      {
        const uint32_t fx = (((cta >> 4) ^ cta) & 3) << 3, dl = O_IN - O_Z1, st = sbase + O_ST + 15360 + tid * 16;
        sts4(st, (lo[0] ^ fx) + dl, (lo[1] ^ fx) + dl, (lo[2] ^ fx) + dl, (lo[3] ^ fx) + dl);
        sts4(st + 4096, (lo[4] ^ fx) + dl, (lo[5] ^ fx) + dl, (lo[6] ^ fx) + dl, (lo[7] ^ fx) + dl);
        sts4(st + 8192, (lo[8] ^ fx) + dl, (lo[0] ^ fx) + dl + (kap ? 0 : 288 * 8),
             sbase + O_B3 + wg * 1024 + (l >> 4) * 2048 + (2 * (kap & 24) + (l & 15)) * 16, 0);
      }
    }
    {
      uint32_t sy[6];
#pragma unroll
      for (int i = 0; i < 6; i++) {
        const int rr = 16 * (wp & 3) + g + 8 * (i & 1);
        sy[i] = sbase + O_Y + (t * 584 + 64 * ((3 * wg + (i >> 1) + 63 - rr) % 9) + rr) * 4;
      }
      sts4(sbase + O_ST + tid * 16, movm(tb[0]), movm(tb[2]), movm(tb[1]), movm(tb[3]));
      sts4(sbase + O_ST + 6144 + tid * 16, sy[0], sy[1], sy[2], sy[3]);
      sts2(sbase + O_ST + 12288 + tid * 8, sy[4], sy[5]);
    }
  } else {
    fence_async_smem();
    __syncthreads();
  }

  const unsigned ep = upin(lds(full0 + 248));
  const uint32_t tag16 = tag_of(ep), tag1 = ep & 1;
  auto load_wm = [&](int u) {
    if (wp > 8 && elect()) {
      mbar_expect(full0 + 8 * B_WM, 6144);
      tma2d(sbase + O_NRM + (wp - 9) * 6144, &maps.wm, 16 * u, 192 * (wp - 9), full0 + 8 * B_WM);
    }
    __syncwarp();
  };
  if (R >= 0) {
    const int nl = (col0 + wp < DF_) + (wg < 2 && col0 + wp + 12 < DF_);
    uint4 cf[2][4], G[4];
#pragma unroll
    for (int i = 0; i < 4; i++) {
      cf[0][i] = __ldg(p.tab + TB_P2 + i * 32 + l);
      cf[1][i] = __ldg(p.tab + TB_P2 + (pi ? i : 4 + i) * 32 + l);
      G[i] = __ldg(p.tab + TB_P2 + (8 + i) * 32 + l);
    }
    const uint32_t* zin = sc->z1 + (size_t)R * 5120;
    if (wp == 10) {
      const uint32_t* zu = upin(zin);
      if (elect()) mbar_expect(full0 + 8 * B_Z1, 20480);
      wait_cnt(sc->cnt + C_Z1 + 32 * (pi >> 2), 128 * ep);
      if (elect()) {
        bulk_ld(sbase + O_P2, zu, 20480, full0 + 8 * B_Z1);
      }
      __syncwarp();
    }
    mbar_wait(full0 + 8 * B_FLT, 0);
    float wn[16], wc[16];
#pragma unroll 1
    for (int ln = nl - 1; ln >= 0; ln--) {
      const int col = col0 + wp + 12 * ln, k2 = (57 * col) & 63;
      const bool cj = k2 > 32;
      const float nr = ((col & 31) == 0 && col != 0 && col != 288 ? 0.5f : 1.0f) / ((float)S_ * D_), ni = cj ? -nr : nr;
#pragma unroll
      for (int i = 0; i < 16; i++) wn[i] = wc[i];
#pragma unroll
      for (int cl = 0; cl < 2; cl++) {
        const int v = cl ^ (cj && pi), e = ((v ? xv : xu) & 15) + wp + 12 * ln, sh = e < 32 ? 6 : 5;
        const uint32_t base = sbase + O_RAW + v * 12288 + (e < 32 ? 2 * e : 8192 - 64 + 2 * e), msk = e < 32 ? 0x30 : 0x10;
        const int dm = v ? (cj || pi ? -1 : 0) : 0;
#pragma unroll
        for (int tt = 0; tt < 4; tt++) {
          const int kc = g + 64 * (tt >> 1) + 16 * t + 8 * (tt & 1);
          uint32_t a = base + ((((cj ? -kc : kc) + dm) & 127) << sh);
          a ^= (a >> 3) & msk;
          wc[4 * tt + 2 * cl] = lds_bf(a) * nr; wc[4 * tt + 2 * cl + 1] = lds_bf(a + 24576) * ni;
        }
      }
    }
    const float al = __uint_as_float(pin((pi ? 0x3f800000u : 0u) + (l >> 5)));
    const uint32_t tagv = pin(tag1 + (l >> 5));
    uint32_t off = pin(l * 160 + ((wp ^ (g & 3)) << 3));
    uint32_t offo = pin(sbase + O_P2 + 20480 + off - 64 * l), po = 3072;
    unsigned* hz2 = pin(sc->cnt + C_Z2);
    const uint32_t do2 = pin(12288 - 32 * l);
    const CUtensorMap* mz2 = upin(&maps.z2[wp == 0]);
    const uint32_t sz2 = upin(sbase + O_P2 + 20480 + (wp ? 0 : 12288)), cz2 = upin(40 * R + (wp ? 0 : 24));
    mbar_wait(full0 + 8 * B_Z1, 0);
    if (wg == 2) load_wm(72 + mu);
    uint2 v[4], v2[4];
    const uint32_t o2 = nl > 1 ? 96 : 0;
#pragma unroll
    for (int i = 0; i < 4; i++) { v[i] = lds2(sbase + O_P2 + off + i * 5120); v2[i] = lds2(sbase + O_P2 + off + o2 + i * 5120); }
    auto bad2 = [&]() {
      return any(or3(or3(diff2(v[0].x, v[1].x, tagv), diff2(v[2].x, v[3].x, tagv), diff2(v2[0].x, v2[1].x, tagv)), diff2(v2[2].x, v2[3].x, tagv), 0) & 1);
    };
    if (__builtin_expect(bad2() && nl, 0)) {
      int it = 0;
      do {
#pragma unroll
        for (int i = 0; i < 4; i++) {
          v[i] = ld_rlx2(reinterpret_cast<const uint8_t*>(zin) + off + i * 5120);
          v2[i] = ld_rlx2(reinterpret_cast<const uint8_t*>(zin) + off + o2 + i * 5120);
        }
      } while (bad2() && ++it < SPIN_MAX);
    }
#pragma unroll 1
    for (int ln = 0; ln < nl; ln++, offo += do2, po = 2048) {
      float d[4][4];
      uint32_t A[8];
#pragma unroll
      for (int h = 0; h < 2; h++) {
        mma16<false>(d[2 * h], cf[0][0].x, cf[0][0].y, cf[0][0].z, cf[0][0].w, v[h].x, v[2 + h].x);
        mma16<false>(d[2 * h + 1], cf[1][0].x, cf[1][0].y, cf[1][0].z, cf[1][0].w, v[h].y, v[2 + h].y);
      }
      if (ln) { fence_async_smem(); bar_arrive(15, NTHR); }
#pragma unroll
      for (int h = 0; h < 2; h++)
#pragma unroll
        for (int L = 0; L < 2; L++) {
          const uint4 tw = cf[L][2 + h];
          const float* z = d[2 * h + L];
          const float2 z0 = cmul(make_float2(z[0], z[2]), make_float2(__uint_as_float(tw.x), __uint_as_float(tw.y)));
          const float2 z1 = cmul(make_float2(z[1], z[3]), make_float2(__uint_as_float(tw.z), __uint_as_float(tw.w)));
          A[4 * h + L] = pack_bf16(z0.x, z0.y); A[4 * h + 2 + L] = pack_bf16(z1.x, z1.y);
        }
#pragma unroll
      for (int tt = 0; tt < 4; tt++) {
        mma16<false>(d[tt], A[0], A[1], A[2], A[3], G[tt].x, G[tt].y);
        mma16<true>(d[tt], A[4], A[5], A[6], A[7], G[tt].z, G[tt].w);
      }
#pragma unroll
      for (int tt = 0; tt < 4; tt++) {
        const float ar = d[tt][0], aj = d[tt][1], br = d[tt][2], bj = d[tt][3];
        const float2 y1 = cmul(make_float2(fmaf(-al, bj, ar), fmaf(al, br, aj)), make_float2(wc[4 * tt], wc[4 * tt + 1]));
        const float2 y2 = cmul(make_float2(fmaf(al, ar, bj), fmaf(al, aj, -br)), make_float2(wc[4 * tt + 2], wc[4 * tt + 3]));
        A[2 * tt] = pack_bf16(fmaf(al, y2.x, y1.x), fmaf(-al, y2.y, -y1.y));
        A[2 * tt + 1] = pack_bf16(fmaf(al, y1.y, -y2.y), fmaf(al, y1.x, -y2.x));
      }
#pragma unroll
      for (int i = 0; i < 16; i++) wc[i] = wn[i];
#pragma unroll
      for (int i = 0; i < 4; i++) v[i] = v2[i];
#pragma unroll
      for (int tt = 0; tt < 4; tt++) {
        mma16<false>(d[tt], A[0], A[1], A[2], A[3], G[tt].x, G[tt].y);
        mma16<true>(d[tt], A[4], A[5], A[6], A[7], G[tt].z, G[tt].w);
      }
#pragma unroll
      for (int h = 0; h < 2; h++)
#pragma unroll
        for (int L = 0; L < 2; L++) {
          const uint4 tw = cf[L][2 + h];
          const float2 z0 = cmul(make_float2(d[2 * h][2 * L], d[2 * h][2 * L + 1]), make_float2(__uint_as_float(tw.x), __uint_as_float(tw.y)));
          const float2 z1 = cmul(make_float2(d[2 * h + 1][2 * L], d[2 * h + 1][2 * L + 1]), make_float2(__uint_as_float(tw.z), __uint_as_float(tw.w)));
          A[4 * h + 2 * L] = movm(pack_bf16(z0.x, z1.x)); A[4 * h + 2 * L + 1] = movm(pack_bf16(z0.y, z1.y));
        }
#pragma unroll
      for (int h = 0; h < 2; h++) {
        mma16<false>(d[0], cf[0][1].x, cf[0][1].y, cf[0][1].z, cf[0][1].w, A[4 * h], A[4 * h + 1]);
        mma16<false>(d[1], cf[1][1].x, cf[1][1].y, cf[1][1].z, cf[1][1].w, A[4 * h + 2], A[4 * h + 3]);
#pragma unroll
        for (int e = 0; e < 2; e++)
          sts2(offo + (2 * h + e) * po, set_tag(pack_bf16(d[0][e], d[0][2 + e]), tagv), pack_bf16(d[1][e], d[1][2 + e]));
      }
    }
    fence_async_smem();
    if (nl < 2 && wp != 8) bar_arrive(15, NTHR);
    if (wp) bar_arrive(6, NTHR);
    if (!(wp & 7)) {
      bar_sync(wp ? 15 : 6, NTHR);
      if (elect()) tma_st2d(mz2, sz2, cz2, 0);
      if (wp == 0 && elect()) red_add(hz2, 1);
      if (wp == 0) bulk_commit_wait();
      __syncwarp();
    }
  }
  if (wg == 2) {
#pragma unroll 1
    for (int u = 72 + mu, k = 0; u < 216; u += NCTA, k ^= 1) {
      if (R < 0) { fence_async_smem(); bar_sync(4, 128); load_wm(u); }
      mod_unit(sc, u, t128, sbase + O_NRM, full0 + 8 * B_WM, k, red + 256 - 256 * k, tag16);
    }
    fence_async_smem();
  }

  const int grp = bx / 11, m1 = bx - 11 * grp;
  const bool helper = (m1 & 3) == 3;
  const int f1 = 384 * grp + (helper ? 192 : 128) * (m1 >> 2);
  const int d1 = 160 * (m1 & 3), flip = m1 >= 7;
  const int a1bytes = helper ? 24576 : 16384;
  auto load_a1 = [&](int st, int kb) {
    mbar_expect(full0 + 8 * st, a1bytes);
    tma4d_ef(sbase + st * STAGE, helper ? &maps.w1b : &maps.w1a, 4 * (kb >> 3), 16 * (kb & 7), f1 >> 6, full0 + 8 * st);
  };

  uint32_t bia[4];
  if (wg < 2) {
    const int fa = f1 + (helper ? 128 : 64) * (wg ^ flip) + 16 * (wp & 3) + g, fb = helper ? f1 + 64 + 16 * (wp & 3) + g : fa;
#pragma unroll
    for (int i = 0; i < 4; i++) asm volatile("ld.global.nc.u16 %0, [%1];" : "=r"(bia[i]) : "l"(p.b1 + (i < 2 ? fa : fb) + 8 * (i & 1)) : "memory");
  }
  if (rows) {
#pragma unroll
    for (int kk = 0; kk < 4; kk++) af[kk] = __ldg(p.tab + TB_E + kk * 128 + t128);
    const uint4 c0 = lds4(sbase + O_ST + tid * 16), c1 = lds4(sbase + O_ST + 6144 + tid * 16);
    const uint2 c2 = lds2(sbase + O_ST + 12288 + tid * 8);
    const uint32_t tc[4] = {c0.x, c0.y, c0.z, c0.w}, sy[6] = {c1.x, c1.y, c1.z, c1.w, c2.x, c2.y};
    const uint32_t l8 = pin(8 * l), syl = pin(sbase + O_Y + wp * 2336 + 8 * l);
    uint32_t sh3[3], ham[3];
#pragma unroll
    for (int k = 0; k < 3; k++) {
      const int pos = k && (l >> 4) == k - 1 ? 2 * (l & 6) + ((l >> 2) & 2) + (l & 1) : l & 15;
      const int sw = 2 * cta + ((wp >> 1) & 1), ph = pos ^ ((sw & 3) << 2);
      sh3[k] = pin((l >> 4) * 256 + (wp & 3) * 64 + ph * 4);
      ham[k] = pin(((ph ^ sw) & 7) == 0 ? ~1u : ~0u);
    }
    unsigned* const hh3 = upin(sc->cnt + C_H3 + (cta >> 4));
    uint8_t* const h3g = pin(sc->h3 + (cta >> 4) * (18 * 4096) + (cta & 15) * 256 + (l >> 4) * 3840);
    const int slot = 4 * (cta >> 4) + ((cta >> 1) & 3) + 32 * (2 * ((cta >> 3) & 1) + (cta & 1));
    const uint32_t* zin = sc->z2 + (size_t)slot * 4800;
    if (wg == 2) {
      {
        uint4 v[4];
        const int i3 = min(t128 + 384, 431);
        int it = 0;
        while (true) {
          uint32_t bad = 0;
#pragma unroll
          for (int k = 0; k < 4; k++) v[k] = ld_rlx4(sc->mod + 4 * (k < 3 ? t128 + 128 * k : i3));
#pragma unroll
          for (int k = 0; k < 4; k++) {
            v[k].x ^= tag16; v[k].y ^= tag16; v[k].z ^= tag16; v[k].w ^= tag16;
            bad |= v[k].x | v[k].y | v[k].z | v[k].w;
          }
          if (!any(bad & 0xffffu) || ++it > SPIN_MAX) break;
        }
#pragma unroll
        for (int k = 0; k < 4; k++) sts4(sbase + O_MOD + 16 * (k < 3 ? t128 + 128 * k : i3), v[k].x, v[k].y, v[k].z, v[k].w);
      }
      bulk_commit_wait();
      bar_sync(10, NTHR);
      mbar_wait(full0 + 8 * B_Z2, 0);
      if (elect()) {
        load_a1(wp - 8, wp - 8);
      }
      __syncwarp();
    } else {
      const uint4 e0 = lds4(sbase + O_ST + 15360 + tid * 16), e1 = lds4(sbase + O_ST + 19456 + tid * 16), e2 = lds4(sbase + O_ST + 23552 + tid * 16);
      const uint32_t li[9] = {e0.x, e0.y, e0.z, e0.w, e1.x, e1.y, e1.z, e1.w, e2.x}, lx = e2.y, sb3 = e2.z;
      bar_arrive(10, NTHR);
      if (wp == 1) {
        const uint32_t* zu = upin(zin);
        if (elect()) mbar_expect(full0 + 8 * B_Z2, 19200);
        wait_cnt(sc->cnt + C_Z2, 120 * ep);
        if (elect()) {
          bulk_ld(sbase + O_IN, zu, 19200, full0 + 8 * B_Z2);
        }
        __syncwarp();
      }
      mbar_wait(full0 + 8 * B_Z2, 0);
      uint2 v[10];
#pragma unroll
      for (int k1 = 0; k1 < 10; k1++) v[k1] = lds2(k1 < 9 ? li[k1] : lx);
      float2 za[9], zb[9];
      int it = 0;
#pragma unroll 1
      while (true) {
      const uint32_t bad = or3(or3(diff2(v[0].x, v[1].x, tag1), diff2(v[2].x, v[3].x, tag1), diff2(v[4].x, v[5].x, tag1)), diff2(v[6].x, v[7].x, tag1), diff2(v[8].x, v[9].x, tag1));
#pragma unroll
      for (int i = 0; i < 9; i++) { za[i] = make_float2(bf_lo(v[i].x), bf_hi(v[i].x)); zb[i] = make_float2(bf_lo(v[i].y), bf_hi(v[i].y)); }
      if ((wp & 3) == wg) {
        const float sp = g ? 0.f : 1.f;
#pragma unroll
        for (int k = 1; k < 5; k++) {
          float2 a = za[k], b = za[9 - k];
          za[k] = make_float2(fmaf(-sp, b.x, a.x), fmaf(sp, b.y, a.y)); za[9 - k] = make_float2(fmaf(sp, a.x, b.x), fmaf(-sp, a.y, b.y));
          a = zb[k]; b = zb[9 - k];
          zb[k] = make_float2(fmaf(-sp, b.x, a.x), fmaf(sp, b.y, a.y)); zb[9 - k] = make_float2(fmaf(sp, a.x, b.x), fmaf(-sp, a.y, b.y));
        }
        za[0].y = g ? za[0].y : bf_lo(v[9].x); zb[0].y = g ? zb[0].y : bf_lo(v[9].y);
      }
      dft9(za); dft9(zb);
#pragma unroll
      for (int n = 0; n < 8; n += 2) {
        const int i0 = (9 - n) % 9, i1 = 8 - n;
        stmatrix4(sb3 + n * 2048, pack_bf16(za[i0].x, zb[i0].x), pack_bf16(za[i0].y, zb[i0].y), pack_bf16(za[i1].x, zb[i1].x), pack_bf16(za[i1].y, zb[i1].y));
      }
      stmatrix2(sb3 + 8 * 2048, pack_bf16(za[1].x, zb[1].x), pack_bf16(za[1].y, zb[1].y));
      if (__builtin_expect(!any(bad & 1) || ++it > SPIN_MAX, 1)) break;
#pragma unroll
      for (int k1 = 0; k1 < 10; k1++) v[k1] = ld_rlx2(reinterpret_cast<const uint8_t*>(zin) + (pin(k1 < 9 ? li[k1] : lx) - (sbase + O_IN)));
      }
      fence_async_smem();
    }
    __syncthreads();
    float acc[24];
    const uint32_t db = (((sbase + O_B3 + wg * 6144) & 0x3FFFF) >> 4) | ((128 >> 4) << 16);
    wg_fence();
#pragma unroll
    for (int kk = 0; kk < 4; kk++) wgmma_rs_48(acc, af[kk].x, af[kk].y, af[kk].z, af[kk].w, db + kk * 16, 1024 >> 4, kk);
    wg_commit();
    uint32_t ga[9];
    if (wg < 2) {
#pragma unroll
      for (int i = 0; i < 9; i++) { const uint2 v = lds2(l8 + sbase + O_MOD + 256 * i); ga[i] = __byte_perm(v.x, v.y, 0x7632); }
    }
    wg_wait<0>();
    reg_fence(acc);
#pragma unroll
    for (int i = 0; i < 3; i++) {
      const float* a = &acc[8 * i];
      const uint32_t a0 = pack_bf16(a[0], a[1]), a1 = pack_bf16(a[2], a[3]), a2 = pack_bf16(a[4], a[5]), a3 = pack_bf16(a[6], a[7]);
#pragma unroll
      for (int jh = 0; jh < 2; jh++) {
        float y[4];
        mma16<false>(y, a0, a1, a2, a3, tc[2 * jh], tc[2 * jh + 1]);
        sts(sy[2 * i] + jh * (4 * 584 * 4), pack_bf16(y[0], y[1]));
        sts(sy[2 * i + 1] + jh * (4 * 584 * 4), pack_bf16(y[2], y[3]));
      }
    }
    if (wg == 2) bar_arrive(7, NTHR); else bar_sync(7, NTHR);
    if (wg) bar_sync(15, NTHR);
    if (wg < 2) {
      uint2 y[9], sh[9], sw[9];
#pragma unroll
      for (int i = 0; i < 9; i++) y[i] = lds2(syl + 256 * i);
      uint32_t sel = 0x5410, sto = sbase + O_B3 + wg * 9216;
#pragma unroll 1
      for (int e = 0; e < 2; e++, sel = 0x7632, sto += 4608) {
        float a[18];
#pragma unroll
        for (int i = 0; i < 9; i++) {
          const uint32_t x1 = hfma2(ga[i], __byte_perm(y[i].x, y[i].y, sel), xr[i]);
          xr[i] = xr[9 + i]; xr[9 + i] = x1;
          a[2 * i] = bf_lo(x1); a[2 * i + 1] = bf_hi(x1);
        }
#pragma unroll
        for (int i = 0; i < 9; i++) { lds2_if(!e, sh[i], l8 + sbase + O_MOD + 4 * D_ + 256 * i); lds2_if(!e, sw[i], l8 + sbase + O_MOD + 8 * D_ + 256 * i); }
        float oa, ra;
        ln_stats1(a, 1.0f, oa, ra);
#pragma unroll
        for (int i = 0; i < 9; i++) {
          a[2 * i] = fmaf(fmaf(a[2 * i], ra, oa), __uint_as_float(sw[i].x), __uint_as_float(sh[i].x));
          a[2 * i + 1] = fmaf(fmaf(a[2 * i + 1], ra, oa), __uint_as_float(sw[i].y), __uint_as_float(sh[i].y));
        }
        ln_stats1(a, 0.5f, oa, ra);
        uint32_t hv[9];
#pragma unroll
        for (int i = 0; i < 9; i++) hv[i] = bitsel(pack_bf16(fmaf(a[2 * i], ra, oa), fmaf(a[2 * i + 1], ra, oa)), ham[i == 2 ? 1 : i == 6 ? 2 : 0], tag1);
        if (!(wg | e)) {
          if (elect()) red_add(hh3, 1);
#pragma unroll
          for (int i = 0; i < 9; i++) asm volatile("st.global.b32 [%0], %1;" ::"l"(h3g + sh3[i == 2 ? 1 : i == 6 ? 2 : 0] + i * 8192), "r"(hv[i]) : "memory");
          bar_arrive(15, NTHR);
        } else {
#pragma unroll
          for (int i = 0; i < 9; i++) sts(sto + sh3[i == 2 ? 1 : i == 6 ? 2 : 0] + i * 512, hv[i]);
        }
        if (!e) bar_arrive(8, 288);
      }
      fence_async_smem();
      bar_arrive(9, 288);
    }
  }

  const bool g2 = rows;
  const int z2 = cta, r = z2 >> 6;
  const int s2 = 128 * ((z2 >> 2) & 15), d2 = 144 * (z2 & 3);
  constexpr int ST0 = 32 % NST;
  const bool first = helper || m1 < W0N;

  if (wg == 2) {
    asm volatile("setmaxnreg.dec.sync.aligned.u32 40;");
    const int l = lane_id(), g = l >> 2;
    auto load_b = [&](bool second, int i, int st) {
      const uint32_t lb = full0 + 8 * (B_LAND + st), bytes = second ? 18432 : STAGE - a1bytes;
      mbar_expect(lb, bytes);
      bulk_ld(sbase + (second ? st * STAGE2 + 16384 : st * STAGE + a1bytes),
              second ? sc->u + ((size_t)(36 * r + kb2_order(i)) * D_ + d2) * 128 : sc->h3 + ((size_t)(i * 18 + (d1 >> 5)) << 12), bytes, lb);
    };
    if (wp == 8) {
      int st = rows ? 4 : 0, ph = 1;
#pragma unroll 1
      for (int kb = st; kb < 32; kb++) {
        if (rows && (kb >> 1) == 2) mbar_wait(full0 + 8 * (B_S4 - 4 + kb), 0);
        mbar_wait(empty0 + 8 * st, ph);
        if (elect()) {
          load_a1(st, kb);
        }
        __syncwarp();
        ring_next<false>(st, ph);
      }
      if (g2) {
        st++;
#pragma unroll 1
        for (int i = 0; i < 36; i++) {
          if (i == HOLDA) mbar_wait(full0 + 8 * B_GO, 0);
          mbar_wait(empty0 + 8 * st, ph);
          if (elect()) {
            mbar_expect(full0 + 8 * st, 16384);
            tma3d_ef(sbase + st * STAGE2, &maps.w2, 64 * (36 * r + kb2_order(i)), s2 >> 6, full0 + 8 * st);
          }
          __syncwarp();
          ring_next<true>(st, ph);
        }
      }
    } else if (wp >= 10) {
      const int sw = wp - 10;
      if (sw) {
        if (rows) {
          bar_sync(8, 288);
          mbar_wait(full0, 0);
          if (elect()) mbar_arrive(full0 + 8 * B_S4);
          bar_sync(9, 288);
          if (elect()) tma_st3d(&maps.h3, sbase + O_B3 + 4608, 64 * (cta & 15), 18 * (cta >> 4), 1);
          bulk_commit_wait();
          if (elect()) {
            red_add(sc->cnt + C_H3 + (cta >> 4) + 8, 4);
            mbar_arrive(full0 + 8 * B_S5);
            asm volatile("fence.acq_rel.gpu;" ::: "memory");
            red_add(&sc->cnt[C_X + 64], 1);
          }
          __syncwarp();
        }
        if (g2) {
          sts(sbase + O_GB + 288 + 4 * l, ld_nc(p.b2 + s2 + 64 * (r ^ 1) + 2 * l));
          uint2 v[3];
          int it = 0;
          do {
#pragma unroll
            for (int i = 0; i < 3; i++) v[i] = ld_rlx2(sc->mod + 3 * D_ + d2 + 2 * min(l + 32 * i, 71));
          } while (any(or3(diff2(v[0].x, v[0].y, tag16), diff2(v[1].x, v[1].y, tag16), diff2(v[2].x, v[2].y, tag16)) & 0xffffu) && ++it < SPIN_MAX);
#pragma unroll
          for (int i = 0; i < 3; i++) sts(sbase + O_GB + 4 * min(l + 32 * i, 71), __byte_perm(v[i].x, v[i].y, 0x7632));
          __syncwarp();
        }
        wait_cnt<true>(&sc->cnt[C_X + 64], 128 * ep);
        if (elect()) mbar_arrive(full0 + 8 * B_X);
        __syncwarp();
      }
      uint32_t lph = 0;
      auto check_tiles = [&](bool second, int n, int st, uint32_t o1, uint32_t d2nd) {
        const uint32_t b1 = pin(sbase + o1), b2 = pin(sbase + o1 + d2nd);
        int i = 0, it = 0;
#pragma unroll 1
        do {
          const uint32_t so = st * (second ? STAGE2 : STAGE);
          mbar_wait(full0 + 8 * (B_LAND + st), (lph >> st) & 1);
          lph ^= 1u << st;
          uint32_t v[20];
#pragma unroll
          for (int k = 0; k < 20; k++) if (!second || k < 10 || k >= 12) v[k] = lds(k < 12 ? b1 + so + k * 1024 : b2 + so + (k - 12) * 1024); else v[k] = tag1;
#pragma unroll
          for (int k = 0; k < 10; k++) v[k] = diff2(v[2 * k], v[2 * k + 1], tag1);
          const uint32_t bad = or3(or3(or3(v[0], v[1], v[2]), or3(v[3], v[4], v[5]), v[6]), v[7], or3(v[8], v[9], 0));
          if (__builtin_expect(any(bad & 1) && ++it < SPIN_MAX, 0)) {
            fence_async_smem();
            __syncwarp();
            if (elect()) load_b(second, i, st);
            __syncwarp();
            continue;
          }
          if (elect()) mbar_arrive(full0 + 8 * st);
          if (++st == NST) st = 0;
          i++;
        } while (i < n);
      };
      if (!sw) check_tiles(false, NV1, 0, a1bytes + l * 32 + (l >> 2) * 4, helper ? 4096 : 12288);
      if (sw) {
#pragma unroll 1
        for (int k = 0; k < 2; k++) {
          bar_sync(13 + k, 160);
          if (helper || (first && !k)) continue;
          const uint32_t stg = sbase + (k ? O_U1 : ST0 * STAGE);
          const int kb = (f1 >> 6) + (k ^ flip);
          uint8_t* const ug = sc->u + ((size_t)kb * D_ + d1) * 128;
          if (g2) mbar_wait(full0 + 8 * B_GO, 0);
          if (first) pause(10 * TRK0);
#pragma unroll 1
          for (int i = 0; i < 20480; i += 2048) {
            if (elect()) bulk_st(ug + i, stg + i, 2048);
            pause(k ? TRKC : TRK0);
          }
          if (elect()) red_add(sc->cnt + C_U + kb2_pos(kb), 4);
          bulk_commit_wait();
          if (elect()) { if (!k) mbar_arrive(empty0 + 8 * ST0); }
          __syncwarp();
        }
        if (elect()) { asm volatile("fence.acq_rel.gpu;" ::: "memory"); red_add(&sc->cnt[C_X], 1); }
        __syncwarp();
      }
      if (g2) {
        if (!sw) check_tiles(true, NV2, 3, 16384 + l * 32 + g * 4, 10240);
        else {
          wait_cnt<true>(&sc->cnt[C_X], NCTA * ep);
          if (elect()) mbar_arrive(full0 + 8 * B_X);
          if (cta == 0) sc->cnt[C_EP + l] = ep;
          __syncwarp();
        }
      }
      __syncwarp();
    } else {
      uint32_t ready = 0;
      int st = 0, ph = 1;
#pragma unroll 1
      for (int kb = 0; kb < 32; kb++) {
        const uint8_t* src = upin(sc->h3 + ((size_t)(kb * 18 + (d1 >> 5)) << 12));
        const uint32_t dst = upin(sbase + st * STAGE + a1bytes), lb = full0 + 8 * ((kb < NV1 ? B_LAND : 0) + st);
        if (kb == NV1) { mbar_wait(full0 + 8 * B_X, 0); fence_async_glb(); ready = ~0u; }
        if (rows && (kb >> 1) == 2) mbar_wait(full0 + 8 * (B_S4 - 4 + kb), 0);
        mbar_wait(empty0 + 8 * st, ph);
        if (elect()) mbar_expect(lb, STAGE - a1bytes);
        wait_flags(sc->cnt + C_H3 + l, (kb & 7) + (kb < 8 ? 0 : 8), 64 * ep, ready);
        if (elect()) bulk_ld(dst, src, STAGE - a1bytes, lb);
        ring_next<false>(st, ph);
      }
      if (g2) {
        ready = 0;
        st++;
#pragma unroll 1
        for (int i = 0; i < 36; i++) {
          const int kb = kb2_order(i);
          const uint8_t* src = upin(sc->u + ((size_t)(36 * r + kb) * D_ + d2) * 128);
          const uint32_t dst = upin(sbase + st * STAGE2 + 16384), lb = full0 + 8 * ((i < NV2 ? B_LAND : 0) + st);
          if (i == NV2) { mbar_wait(full0 + 8 * B_X, 1); fence_async_glb(); ready = ~0u; }
          mbar_wait(empty0 + 8 * st, ph);
          if (elect()) mbar_expect(lb, 18432);
          wait_flags(sc->cnt + C_U + 64 * r + l, i & 31, 16 * ep, ready);
          if (elect()) {
            bulk_ld(dst, src, 18432, lb);
            if (i == 0) mbar_arrive(full0 + 8 * B_GO);
          }
          ring_next<true>(st, ph);
        }
      }
    }
  } else {
    asm volatile("setmaxnreg.inc.sync.aligned.u32 232;");
    const int wgu = wg;
    constexpr uint32_t sb4 = sbase >> 4;
    const int w = wp & 3;
    Ring rg = {0, 0};
    const int direct = helper || (first && !wg), kbA = (f1 >> 6) + (helper ? 2 : 1) * (wg ^ flip), kbB = (f1 >> 6) + 1;
    const int ud1 = helper ? (kbB - kbA) * (D_ * 128) - 3 * 4096 : 0;
    uint32_t ad, um0, um1, eh;
    uint8_t* ug0;
    unsigned* uh;
    auto side1 = [&]() {
      const int l = lane_id(), g = l >> 2, t = l & 3;
      if (rows) {
        uint32_t* const x1p = p.out + (size_t)(cta + 128 * (w + 8 * wg)) * 288 + l;
#pragma unroll
        for (int i = 0; i < 9; i++) { x1p[32 * i] = xr[i]; x1p[512 * 288 + 32 * i] = xr[9 + i]; }
      }
      const uint32_t uo = (t >> 1) * 2048 + (16 * w + g) * 32 + (((t ^ (g >> 2)) & 1) << 4);
      ad = sbase + (wg ? O_U1 : ST0 * STAGE) + uo;
      ug0 = sc->u + ((size_t)kbA * D_ + d1) * 128 + uo;
      uh = sc->cnt + C_U + kb2_pos(l ? kbB : kbA);
      eh = direct && !helper && !l;
      const bool utg = ((t ^ (g >> 2) ^ w) & 1) == 0;
      um0 = utg && g < 4 ? ~1u : ~0u; um1 = utg && g >= 4 ? ~1u : ~0u;
    };
    float acc[96];
    constexpr uint32_t LA = (8192 >> 4) << 16, LB = (4096 >> 4) << 16;
    if (!helper) gemm_main<0>(acc, sb4 + (wgu ^ flip) * 512 + LA, 0, sb4 + 1024 + LB, wgu, rg, first ? NST : NST - 1, bia, side1);
    else {
      float ac2[96];
      gemm_main<1>(ac2, sb4 + (wgu ^ flip) * 1024 + LA, sb4 + 512 + LA, sb4 + 1536 + LB, wgu, rg, NST - 1, bia, side1);
#pragma unroll
      for (int i = 0; i < 96; i++) asm volatile("mov.b32 %0, %1;" : "=f"(acc[i]) : "f"(ac2[i]));
    }
    {
      float tp[2] = {0.f, 0.f};
#pragma unroll
      for (int j = 0; j < 12; j++) {
        const float* a = &acc[16 * (j >> 1) + 2 * (j & 1)];
        const float k3 = j < 2 ? GK3 : fmaf(tp[j & 1], 0.0f, GK3);
        uint32_t o[4];
#pragma unroll
        for (int e = 0; e < 4; e++) {
          const float h0 = a[4 * e], h1 = a[4 * e + 1];
          float z0 = h0 * fmaf(h0 * k3, h0, GK1), z1 = h1 * fmaf(h1 * k3, h1, GK1);
          asm("tanh.approx.f32 %0, %0;" : "+f"(z0));
          asm("tanh.approx.f32 %0, %0;" : "+f"(z1));
          if (e == 3) tp[j & 1] = z0;
          o[e] = pack_bf16(fmaf(h0, z0, h0), fmaf(h1, z1, h1));
          if ((e >> 1) == (j & 1)) o[e] = bitsel(o[e], (e & 1) ? um1 : um0, tag1);
        }
        if (j == EH) asm volatile("{\n.reg .pred p;\nsetp.ne.u32 p, %1, 0;\n@p red.relaxed.gpu.global.add.u32 [%0], 1;\n}" ::"l"(uh), "r"(eh) : "memory");
        asm volatile("{\n.reg .pred p;\nsetp.ne.u32 p, %6, 0;\n@p st.global.v4.b32 [%0], {%2,%3,%4,%5};\n@!p st.shared.v4.b32 [%1], {%2,%3,%4,%5};\n}"
                     ::"l"(ug0 + (j < 6 ? 0 : ud1) + (j >> 1) * 4096 + (j & 1) * 256), "r"(ad + (j >> 1) * 4096 + (j & 1) * 256),
                       "r"(o[0]), "r"(o[1]), "r"(o[2]), "r"(o[3]), "r"(direct) : "memory");
        if ((j == 5 && helper && !wgu) || (j == 9 && !helper)) break;
      }
      if (!direct) fence_async_smem();
      else if (l <= wgu && helper) red_add(uh, 1);
      __syncwarp();
      bar_arrive(13 + wgu, 160);
    }
    if (g2) {
      const int mb = wgu ^ r;
      const int odd = z2 & 1;
      uint32_t bi2[4] = {0, 0, 0, 0};
      uint4 gq[4];
      uint2 gs;
      {
        if (wgu) { bi2[0] = __float_as_uint(lds_bf(sbase + O_GB + 288 + 2 * (16 * w + g))) >> 16; bi2[1] = __float_as_uint(lds_bf(sbase + O_GB + 288 + 16 + 2 * (16 * w + g))) >> 16; }
#pragma unroll
        for (int i = 0; i < 4; i++) gq[i] = lds4(sbase + O_GB + 32 * odd + 64 * i + 16 * t);
        gs = lds2(sbase + O_GB + (odd ? 0 : 256) + 8 * t);
      }
      uint32_t* const ob = p.out + (size_t)(s2 + 64 * mb + 16 * w + g) * 288 + (d2 >> 1);
      uint32_t* const oq = pin(ob + 8 * odd + 4 * t);
      uint32_t* const os = pin(ob + (odd ? 0 : 64) + 2 * t);
      rg.st++;
      gemm_main<3>(acc, sb4 + mb * 512 + LA, 0, sb4 + 1024 + ((2048 >> 4) << 16), wgu, rg, NST, bi2, []() {});
      auto finish = [&](const float* aq, const float* as) {
#pragma unroll
        for (int i = 0; i < 8; i++) {
          const float* a = aq + 16 * (i >> 1) + 2 * (i & 1);
          const uint4 gv = gq[i >> 1];
          red_bf16x8(oq + (i & 1) * 2304 + 16 * (i >> 1), hmul2(gv.x, pack_bf16(a[0], a[1])), hmul2(gv.y, pack_bf16(a[4], a[5])),
                     hmul2(gv.z, pack_bf16(a[8], a[9])), hmul2(gv.w, pack_bf16(a[12], a[13])));
        }
#pragma unroll
        for (int i = 0; i < 2; i++) red_bf16x4(os + i * 2304, hmul2(gs.x, pack_bf16(as[2 * i], as[2 * i + 1])), hmul2(gs.y, pack_bf16(as[2 * i + 4], as[2 * i + 5])));
      };
      if (odd) finish(&acc[8], &acc[0]); else finish(&acc[0], &acc[64]);
      __syncwarp();
    }
  }
}

typedef CUresult (*EncodeFn)(CUtensorMap*, CUtensorMapDataType, cuuint32_t, void*, const cuuint64_t*, const cuuint64_t*, const cuuint32_t*,
                             const cuuint32_t*, CUtensorMapInterleave, CUtensorMapSwizzle, CUtensorMapL2promotion, CUtensorMapFloatOOBfill);

struct Dim { cuuint64_t n, stride; cuuint32_t box; };
template <int RANK>
void make_map(EncodeFn enc, CUtensorMap* m, bool words, int swz, const void* ptr, const Dim (&d)[RANK]) {
  cuuint64_t gd[RANK], gs[RANK];
  cuuint32_t bx[RANK], es[RANK];
  for (int i = 0; i < RANK; i++) { gd[i] = d[i].n; gs[i] = d[i].stride; bx[i] = d[i].box; es[i] = 1; }
  enc(m, words ? CU_TENSOR_MAP_DATA_TYPE_UINT32 : CU_TENSOR_MAP_DATA_TYPE_BFLOAT16, RANK, const_cast<void*>(ptr), gd, gs + 1, bx, es,
      CU_TENSOR_MAP_INTERLEAVE_NONE, static_cast<CUtensorMapSwizzle>(swz),
      swz == 3 ? CU_TENSOR_MAP_L2_PROMOTION_L2_256B : CU_TENSOR_MAP_L2_PROMOTION_NONE, CU_TENSOR_MAP_FLOAT_OOB_FILL_NONE);
}

}

extern "C" void kernel_launch(void* const* d_in, const int* in_sizes, int n_in, void* d_out, int out_size) {
  (void)in_sizes; (void)n_in; (void)out_size;
  static EncodeFn enc = nullptr;
  static void *sptr = nullptr, *tptr = nullptr;
  if (!enc) {
    void* f = nullptr; cudaDriverEntryPointQueryResult qr;
    cudaGetDriverEntryPoint("cuTensorMapEncodeTiled", &f, cudaEnableDefault, &qr);
    enc = reinterpret_cast<EncodeFn>(f);
    cudaFuncSetAttribute(fused_kernel, cudaFuncAttributeMaxDynamicSharedMemorySize, SMEM_BYTES);
    cudaGetSymbolAddress(&sptr, g_s);
    cudaGetSymbolAddress(&tptr, T_TAB);
  }
  Params p;
  p.x = (const __nv_bfloat16*)d_in[0]; p.wr = (const __nv_bfloat16*)d_in[1]; p.wi = (const __nv_bfloat16*)d_in[2];
  p.b1 = (const __nv_bfloat16*)d_in[5]; p.b2 = (const __nv_bfloat16*)d_in[7];
  p.c = (const __nv_bfloat16*)d_in[8]; p.wmod = (const __nv_bfloat16*)d_in[9];
  p.w1 = (const __nv_bfloat16*)d_in[4]; p.w2 = (const __nv_bfloat16*)d_in[6];
  p.out = static_cast<uint32_t*>(d_out); p.s = static_cast<Scratch*>(sptr); p.tab = static_cast<const uint4*>(tptr);
  Maps maps;
  make_map<4>(enc, &maps.w1a, false, 3, p.w1, {{64, 0, 64}, {16, 128 * 2 * F_, 4}, {128, 2 * F_, 16}, {72, 128, 2}});
  make_map<4>(enc, &maps.w1b, false, 3, p.w1, {{64, 0, 64}, {16, 128 * 2 * F_, 4}, {128, 2 * F_, 16}, {72, 128, 3}});
  make_map<3>(enc, &maps.w2, false, 3, p.w2, {{64, 0, 64}, {F_, 2 * S_, 64}, {32, 128, 2}});
  make_map<2>(enc, &maps.z1, true, 0, p.s->z1, {{5120, 0, 40}, {120, 20480, 60}});
  for (int i = 0; i < 2; i++) make_map<2>(enc, &maps.z2[i], true, 0, p.s->z2, {{4800, 0, i ? 16u : 24u}, {128, 19200, 128}});
  for (int i = 0; i < 4; i++) make_map<2>(enc, &maps.wf[i], false, 2 - (i & 1), (i & 2) ? p.wi : p.wr, {{16 * DF_, 0, (i & 1) ? 16u : 32u}, {128, 32 * DF_, 128}});
  make_map<2>(enc, &maps.wm, false, 1, p.wmod, {{6 * D_, 0, 16}, {D_, 12 * D_, 192}});
  make_map<3>(enc, &maps.h3, true, 0, p.s->h3, {{1024, 0, 64}, {144, 4096, 18}, {4, 144 * 4096, 3}});
  fused_kernel<<<NCTA, NTHR, SMEM_BYTES, cudaStreamPerThread>>>(p, maps);
}
```

```cpp
#include <cuda_runtime.h>
#include <cuda_bf16.h>
#include <cuda.h>
#include <stdint.h>

namespace {

constexpr int S_ = 2048, D_ = 576, DF_ = 289, F_ = 4608;
constexpr int NCTA = 132, NTHR = 384;
constexpr int STAGE = 36864, NST = 6;
constexpr int STAGE2 = 34816, O_U1 = NST * STAGE2, O_GB = O_U1 + 20480, O_HALF = O_GB + 512, SMEM_BYTES = 232448;
constexpr uint32_t sbase = 1024, red = sbase + NST * STAGE, full0 = sbase + SMEM_BYTES - 256, empty0 = full0 + 8 * NST;
constexpr int O_NRM = 0, O_B1 = 19456, O_Z1 = 38912, O_P2 = 59392, O_ST = 3 * STAGE;
constexpr int O_RAW = 4 * STAGE;
constexpr int O_IN = 4 * STAGE, O_Y = O_IN + 19456, O_B3 = O_IN + 38912, O_MOD = O_IN + 57856;

__device__ __align__(128) const uint32_t T_TAB[6592] = {
0x3f803f80,0xbf803f80,0x3f803f80,0xbf803f80,0x3f803f80,0xbf803f80,0x3f803f80,0xbf803f80,0x3f803f80,0xbf803f80,0x3f803f80,0xbf803f80,
0x3f803f80,0xbf803f80,0x3f803f80,0xbf803f80,0x3f7f3f80,0xbdc90000,0x3f223f35,0xbf46bf35,0x3f753f7b,0xbe95be48,0x3ef13f0e,0xbf62bf55,
0x3f623f6d,0xbef1bec4,0x3e953ec4,0xbf75bf6d,0x3f463f55,0xbf22bf0e,0x3dc93e48,0xbf7fbf7b,0x3f7b3f80,0xbe480000,0xbe480000,0xbf7bbf80,
0x3f553f6d,0xbf0ebec4,0xbf0ebec4,0xbf55bf6d,0x3f0e3f35,0xbf55bf35,0xbf55bf35,0xbf0ebf35,0x3e483ec4,0xbf7bbf6d,0xbf7bbf6d,0xbe48bec4,
0x3f753f80,0xbe950000,0xbf62bf35,0xbef1bf35,0x3f223f55,0xbf46bf0e,0xbf7fbf7b,0x3dc9be48,0x3dc93ec4,0xbf7fbf6d,0xbf46bf6d,0x3f223ec4,
0xbef1be48,0xbf62bf7b,0xbe95bf0e,0x3f753f55,0x3f6d3f80,0xbec40000,0xbf6dbf80,0x3ec40000,0x3ec43f35,0xbf6dbf35,0xbec4bf35,0x3f6d3f35,
0xbec40000,0xbf6dbf80,0x3ec40000,0x3f6d3f80,0xbf6dbf35,0xbec4bf35,0x3f6d3f35,0x3ec43f35,0x3f623f80,0xbef10000,0xbe95bf35,0x3f753f35,
0x3dc93f0e,0xbf7fbf55,0x3f223e48,0x3f463f7b,0xbf46bec4,0xbf22bf6d,0x3f7f3f6d,0xbdc93ec4,0xbf75bf7b,0x3e95be48,0x3ef13f55,0xbf62bf0e,
0x3f553f80,0xbf0e0000,0x3f0e0000,0x3f553f80,0xbe483ec4,0xbf7bbf6d,0x3f7b3f6d,0xbe483ec4,0xbf7bbf35,0xbe48bf35,0x3e483f35,0xbf7bbf35,
0xbf0ebf6d,0x3f553ec4,0xbf55bec4,0xbf0ebf6d,0x3f463f80,0xbf220000,0x3f7f3f35,0x3dc93f35,0xbef13e48,0xbf62bf7b,0x3e953f55,0xbf75bf0e,
0xbf75bf6d,0x3e95bec4,0xbf62bec4,0xbef1bf6d,0x3dc9bf0e,0x3f7f3f55,0xbf22bf7b,0x3f463e48,0x3f353f80,0xbf350000,0x3f353f80,0xbf350000,
0xbf350000,0xbf35bf80,0xbf350000,0xbf35bf80,0xbf35bf80,0x3f350000,0xbf35bf80,0x3f350000,0x3f350000,0x3f353f80,0x3f350000,0x3f353f80,
0x3f223f80,0xbf460000,0xbdc93f35,0xbf7fbf35,0xbf62be48,0xbef1bf7b,0xbf75bf55,0x3e95bf0e,0xbe95bf6d,0x3f753ec4,0x3ef1bec4,0x3f623f6d,
0x3f7f3f0e,0x3dc93f55,0x3f463f7b,0xbf223e48,0x3f0e3f80,0xbf550000,0xbf550000,0xbf0ebf80,0xbf7bbec4,0xbe48bf6d,0xbe48bf6d,0x3f7b3ec4,
0x3e48bf35,0x3f7b3f35,0x3f7b3f35,0xbe483f35,0x3f553f6d,0xbf0e3ec4,0xbf0e3ec4,0xbf55bf6d,0x3ef13f80,0xbf620000,0xbf75bf35,0x3e95bf35,
0xbf7fbf0e,0x3dc9bf55,0x3f46be48,0x3f223f7b,0x3f22bec4,0x3f463f6d,0x3dc93f6d,0xbf7fbec4,0x3e953f7b,0xbf75be48,0xbf62bf55,0x3ef1bf0e,
0x3ec43f80,0xbf6d0000,0xbec4bf80,0x3f6d0000,0xbf6dbf35,0x3ec4bf35,0x3f6d3f35,0xbec43f35,0x3f6d0000,0x3ec43f80,0xbf6d0000,0xbec4bf80,
0xbec43f35,0xbf6dbf35,0x3ec4bf35,0x3f6d3f35,0x3e953f80,0xbf750000,0x3ef1bf35,0x3f623f35,0xbf46bf55,0x3f22bf0e,0x3dc93f7b,0xbf7fbe48,
0x3f7f3ec4,0xbdc93f6d,0xbf22bf6d,0x3f46bec4,0xbf623e48,0xbef1bf7b,0x3f753f0e,0xbe953f55,0x3e483f80,0xbf7b0000,0x3f7b0000,0x3e483f80,
0xbf0ebf6d,0x3f55bec4,0xbf553ec4,0xbf0ebf6d,0x3f553f35,0xbf0e3f35,0x3f0ebf35,0x3f553f35,0xbf7bbec4,0x3e48bf6d,0xbe483f6d,0xbf7bbec4,
0x3dc93f80,0xbf7f0000,0x3f463f35,0xbf223f35,0xbe95bf7b,0x3f75be48,0xbf62bf0e,0x3ef1bf55,0x3ef13f6d,0xbf623ec4,0x3f753ec4,0xbe953f6d,
0xbf22bf55,0x3f46bf0e,0xbf7fbe48,0x3dc9bf7b,0x3f80,0xbf800000,0x3f80,0xbf800000,0xbf80,0x3f800000,0xbf80,0x3f800000,
0x3f80,0xbf800000,0x3f80,0xbf800000,0xbf80,0x3f800000,0xbf80,0x3f800000,0xbdc93f80,0xbf7f0000,0xbf463f35,0xbf22bf35,
0x3e95bf7b,0x3f753e48,0x3f62bf0e,0x3ef13f55,0xbef13f6d,0xbf62bec4,0xbf753ec4,0xbe95bf6d,0x3f22bf55,0x3f463f0e,0x3f7fbe48,0x3dc93f7b,
0xbe483f80,0xbf7b0000,0xbf7b0000,0x3e48bf80,0x3f0ebf6d,0x3f553ec4,0x3f553ec4,0xbf0e3f6d,0xbf553f35,0xbf0ebf35,0xbf0ebf35,0x3f55bf35,
0x3f7bbec4,0x3e483f6d,0x3e483f6d,0xbf7b3ec4,0xbe953f80,0xbf750000,0xbef1bf35,0x3f62bf35,0x3f46bf55,0x3f223f0e,0xbdc93f7b,0xbf7f3e48,
0xbf7f3ec4,0xbdc9bf6d,0x3f22bf6d,0x3f463ec4,0x3f623e48,0xbef13f7b,0xbf753f0e,0xbe95bf55,0xbec43f80,0xbf6d0000,0x3ec4bf80,0x3f6d0000,
0x3f6dbf35,0x3ec43f35,0xbf6d3f35,0xbec4bf35,0xbf6d0000,0x3ec4bf80,0x3f6d0000,0xbec43f80,0x3ec43f35,0xbf6d3f35,0xbec4bf35,0x3f6dbf35,
0xbef13f80,0xbf620000,0x3f75bf35,0x3e953f35,0x3f7fbf0e,0x3dc93f55,0xbf46be48,0x3f22bf7b,0xbf22bec4,0x3f46bf6d,0xbdc93f6d,0xbf7f3ec4,
0xbe953f7b,0xbf753e48,0x3f62bf55,0x3ef13f0e,0xbf0e3f80,0xbf550000,0x3f550000,0xbf0e3f80,0x3f7bbec4,0xbe483f6d,0x3e48bf6d,0x3f7bbec4,
0xbe48bf35,0x3f7bbf35,0xbf7b3f35,0xbe48bf35,0xbf553f6d,0xbf0ebec4,0x3f0e3ec4,0xbf553f6d,0xbf223f80,0xbf460000,0x3dc93f35,0xbf7f3f35,
0x3f62be48,0xbef13f7b,0x3f75bf55,0x3e953f0e,0x3e95bf6d,0x3f75bec4,0xbef1bec4,0x3f62bf6d,0xbf7f3f0e,0x3dc9bf55,0xbf463f7b,0xbf22be48,
0xbf353f80,0xbf350000,0xbf353f80,0xbf350000,0x3f350000,0xbf353f80,0x3f350000,0xbf353f80,0x3f35bf80,0x3f350000,0x3f35bf80,0x3f350000,
0xbf350000,0x3f35bf80,0xbf350000,0x3f35bf80,0xbf463f80,0xbf220000,0xbf7f3f35,0x3dc9bf35,0x3ef13e48,0xbf623f7b,0xbe953f55,0xbf753f0e,
0x3f75bf6d,0x3e953ec4,0x3f62bec4,0xbef13f6d,0xbdc9bf0e,0x3f7fbf55,0x3f22bf7b,0x3f46be48,0xbf553f80,0xbf0e0000,0xbf0e0000,0x3f55bf80,
0x3e483ec4,0xbf7b3f6d,0xbf7b3f6d,0xbe48bec4,0x3f7bbf35,0xbe483f35,0xbe483f35,0xbf7b3f35,0x3f0ebf6d,0x3f55bec4,0x3f55bec4,0xbf0e3f6d,
0xbf623f80,0xbef10000,0x3e95bf35,0x3f75bf35,0xbdc93f0e,0xbf7f3f55,0xbf223e48,0x3f46bf7b,0x3f46bec4,0xbf223f6d,0xbf7f3f6d,0xbdc9bec4,
0x3f75bf7b,0x3e953e48,0xbef13f55,0xbf623f0e,0xbf6d3f80,0xbec40000,0x3f6dbf80,0x3ec40000,0xbec43f35,0xbf6d3f35,0x3ec4bf35,0x3f6dbf35,
0x3ec40000,0xbf6d3f80,0xbec40000,0x3f6dbf80,0x3f6dbf35,0xbec43f35,0xbf6d3f35,0x3ec4bf35,0xbf753f80,0xbe950000,0x3f62bf35,0xbef13f35,
0xbf223f55,0xbf463f0e,0x3f7fbf7b,0x3dc93e48,0xbdc93ec4,0xbf7f3f6d,0x3f46bf6d,0x3f22bec4,0x3ef1be48,0xbf623f7b,0x3e95bf0e,0x3f75bf55,
0xbf7b3f80,0xbe480000,0x3e480000,0xbf7b3f80,0xbf553f6d,0xbf0e3ec4,0x3f0ebec4,0xbf553f6d,0xbf0e3f35,0xbf553f35,0x3f55bf35,0xbf0e3f35,
0xbe483ec4,0xbf7b3f6d,0x3f7bbf6d,0xbe483ec4,0xbf7f3f80,0xbdc90000,0xbf223f35,0xbf463f35,0xbf753f7b,0xbe953e48,0xbef13f0e,0xbf623f55,
0xbf623f6d,0xbef13ec4,0xbe953ec4,0xbf753f6d,0xbf463f55,0xbf223f0e,0xbdc93e48,0xbf7f3f7b,0x3f803f80,0xbf803f80,0x3f803f80,0xbf803f80,
0x3f803f80,0xbf803f80,0x3f803f80,0xbf803f80,0x3f803f80,0xbf803f80,0x3f803f80,0xbf803f80,0x3f803f80,0xbf803f80,0x3f803f80,0xbf803f80,
0xbdc90000,0xbf7fbf80,0xbf46bf35,0xbf22bf35,0xbe95be48,0xbf75bf7b,0xbf62bf55,0xbef1bf0e,0xbef1bec4,0xbf62bf6d,0xbf75bf6d,0xbe95bec4,
0xbf22bf0e,0xbf46bf55,0xbf7fbf7b,0xbdc9be48,0xbf7bbf80,0x3e480000,0x3e480000,0x3f7b3f80,0xbf55bf6d,0x3f0e3ec4,0x3f0e3ec4,0x3f553f6d,
0xbf0ebf35,0x3f553f35,0x3f553f35,0x3f0e3f35,0xbe48bec4,0x3f7b3f6d,0x3f7b3f6d,0x3e483ec4,0x3e950000,0x3f753f80,0x3ef13f35,0xbf62bf35,
0x3f463f0e,0x3f223f55,0xbdc93e48,0xbf7fbf7b,0x3f7f3f6d,0x3dc93ec4,0xbf22bec4,0xbf46bf6d,0x3f623f7b,0xbef1be48,0xbf75bf55,0xbe95bf0e,
0x3f6d3f80,0xbec40000,0xbf6dbf80,0x3ec40000,0x3ec43f35,0xbf6dbf35,0xbec4bf35,0x3f6d3f35,0xbec40000,0xbf6dbf80,0x3ec40000,0x3f6d3f80,
0xbf6dbf35,0xbec4bf35,0x3f6d3f35,0x3ec43f35,0xbef10000,0xbf62bf80,0x3f753f35,0x3e953f35,0xbf7fbf55,0xbdc9bf0e,0x3f463f7b,0xbf22be48,
0xbf22bf6d,0x3f463ec4,0xbdc93ec4,0xbf7fbf6d,0x3e95be48,0x3f753f7b,0xbf62bf0e,0xbef1bf55,0xbf55bf80,0x3f0e0000,0xbf0e0000,0xbf55bf80,
0x3e48bec4,0x3f7b3f6d,0xbf7bbf6d,0x3e48bec4,0x3f7b3f35,0x3e483f35,0xbe48bf35,0x3f7b3f35,0x3f0e3f6d,0xbf55bec4,0x3f553ec4,0x3f0e3f6d,
0x3f220000,0x3f463f80,0xbdc9bf35,0x3f7f3f35,0x3f623f7b,0xbef13e48,0x3f753f0e,0x3e953f55,0xbe953ec4,0xbf75bf6d,0x3ef13f6d,0xbf62bec4,
0xbf7fbf55,0x3dc9bf0e,0xbf46be48,0xbf22bf7b,0x3f353f80,0xbf350000,0x3f353f80,0xbf350000,0xbf350000,0xbf35bf80,0xbf350000,0xbf35bf80,
0xbf35bf80,0x3f350000,0xbf35bf80,0x3f350000,0x3f350000,0x3f353f80,0x3f350000,0x3f353f80,0xbf460000,0xbf22bf80,0xbf7fbf35,0x3dc9bf35,
0xbef1bf7b,0x3f623e48,0x3e95bf0e,0x3f753f55,0x3f753ec4,0x3e953f6d,0x3f623f6d,0xbef13ec4,0x3dc93f55,0xbf7fbf0e,0xbf223e48,0xbf46bf7b,
0xbf0ebf80,0x3f550000,0x3f550000,0x3f0e3f80,0x3f7b3ec4,0x3e483f6d,0x3e483f6d,0xbf7bbec4,0xbe483f35,0xbf7bbf35,0xbf7bbf35,0x3e48bf35,
0xbf55bf6d,0x3f0ebec4,0x3f0ebec4,0x3f553f6d,0x3f620000,0x3ef13f80,0xbe953f35,0xbf75bf35,0xbdc93f55,0xbf7fbf0e,0xbf22bf7b,0x3f46be48,
0xbf46bf6d,0x3f22bec4,0x3f7f3ec4,0x3dc93f6d,0x3f753e48,0x3e953f7b,0xbef13f0e,0xbf62bf55,0x3ec43f80,0xbf6d0000,0xbec4bf80,0x3f6d0000,
0xbf6dbf35,0x3ec4bf35,0x3f6d3f35,0xbec43f35,0x3f6d0000,0x3ec43f80,0xbf6d0000,0xbec4bf80,0xbec43f35,0xbf6dbf35,0x3ec4bf35,0x3f6d3f35,
0xbf750000,0xbe95bf80,0x3f623f35,0xbef13f35,0x3f22bf0e,0x3f463f55,0xbf7fbe48,0xbdc9bf7b,0xbdc93f6d,0xbf7fbec4,0x3f46bec4,0x3f223f6d,
0xbef1bf7b,0x3f62be48,0xbe953f55,0xbf75bf0e,0xbe48bf80,0x3f7b0000,0xbf7b0000,0xbe48bf80,0x3f0e3f6d,0xbf553ec4,0x3f55bec4,0x3f0e3f6d,
0xbf55bf35,0x3f0ebf35,0xbf0e3f35,0xbf55bf35,0x3f7b3ec4,0xbe483f6d,0x3e48bf6d,0x3f7b3ec4,0x3f7f0000,0x3dc93f80,0x3f22bf35,0x3f463f35,
0xbf753e48,0xbe95bf7b,0xbef13f55,0xbf62bf0e,0x3f62bec4,0x3ef13f6d,0x3e95bf6d,0x3f753ec4,0xbf463f0e,0xbf22bf55,0xbdc93f7b,0xbf7fbe48,
0x3f80,0xbf800000,0x3f80,0xbf800000,0xbf80,0x3f800000,0xbf80,0x3f800000,0x3f80,0xbf800000,0x3f80,0xbf800000,
0xbf80,0x3f800000,0xbf80,0x3f800000,0xbf7f0000,0x3dc9bf80,0xbf22bf35,0x3f46bf35,0x3f753e48,0xbe953f7b,0x3ef13f55,0xbf623f0e,
0xbf62bec4,0x3ef1bf6d,0xbe95bf6d,0x3f75bec4,0x3f463f0e,0xbf223f55,0x3dc93f7b,0xbf7f3e48,0x3e48bf80,0x3f7b0000,0x3f7b0000,0xbe483f80,
0xbf0e3f6d,0xbf55bec4,0xbf55bec4,0x3f0ebf6d,0x3f55bf35,0x3f0e3f35,0x3f0e3f35,0xbf553f35,0xbf7b3ec4,0xbe48bf6d,0xbe48bf6d,0x3f7bbec4,
0x3f750000,0xbe953f80,0xbf623f35,0xbef1bf35,0xbf22bf0e,0x3f46bf55,0x3f7fbe48,0xbdc93f7b,0x3dc93f6d,0xbf7f3ec4,0xbf46bec4,0x3f22bf6d,
0x3ef1bf7b,0x3f623e48,0x3e953f55,0xbf753f0e,0xbec43f80,0xbf6d0000,0x3ec4bf80,0x3f6d0000,0x3f6dbf35,0x3ec43f35,0xbf6d3f35,0xbec4bf35,
0xbf6d0000,0x3ec4bf80,0x3f6d0000,0xbec43f80,0x3ec43f35,0xbf6d3f35,0xbec4bf35,0x3f6dbf35,0xbf620000,0x3ef1bf80,0x3e953f35,0xbf753f35,
0x3dc93f55,0xbf7f3f0e,0x3f22bf7b,0x3f463e48,0x3f46bf6d,0x3f223ec4,0xbf7f3ec4,0x3dc9bf6d,0xbf753e48,0x3e95bf7b,0x3ef13f0e,0xbf623f55,
0x3f0ebf80,0x3f550000,0xbf550000,0x3f0ebf80,0xbf7b3ec4,0x3e48bf6d,0xbe483f6d,0xbf7b3ec4,0x3e483f35,0xbf7b3f35,0x3f7bbf35,0x3e483f35,
0x3f55bf6d,0x3f0e3ec4,0xbf0ebec4,0x3f55bf6d,0x3f460000,0xbf223f80,0x3f7fbf35,0x3dc93f35,0x3ef1bf7b,0x3f62be48,0xbe95bf0e,0x3f75bf55,
0xbf753ec4,0x3e95bf6d,0xbf623f6d,0xbef1bec4,0xbdc93f55,0xbf7f3f0e,0x3f223e48,0xbf463f7b,0xbf353f80,0xbf350000,0xbf353f80,0xbf350000,
0x3f350000,0xbf353f80,0x3f350000,0xbf353f80,0x3f35bf80,0x3f350000,0x3f35bf80,0x3f350000,0xbf350000,0x3f35bf80,0xbf350000,0x3f35bf80,
0xbf220000,0x3f46bf80,0x3dc9bf35,0x3f7fbf35,0xbf623f7b,0xbef1be48,0xbf753f0e,0x3e95bf55,0x3e953ec4,0xbf753f6d,0xbef13f6d,0xbf623ec4,
0x3f7fbf55,0x3dc93f0e,0x3f46be48,0xbf223f7b,0x3f55bf80,0x3f0e0000,0x3f0e0000,0xbf553f80,0xbe48bec4,0x3f7bbf6d,0x3f7bbf6d,0x3e483ec4,
0xbf7b3f35,0x3e48bf35,0x3e48bf35,0x3f7bbf35,0xbf0e3f6d,0xbf553ec4,0xbf553ec4,0x3f0ebf6d,0x3ef10000,0xbf623f80,0xbf753f35,0x3e95bf35,
0x3f7fbf55,0xbdc93f0e,0xbf463f7b,0xbf223e48,0x3f22bf6d,0x3f46bec4,0x3dc93ec4,0xbf7f3f6d,0xbe95be48,0x3f75bf7b,0x3f62bf0e,0xbef13f55,
0xbf6d3f80,0xbec40000,0x3f6dbf80,0x3ec40000,0xbec43f35,0xbf6d3f35,0x3ec4bf35,0x3f6dbf35,0x3ec40000,0xbf6d3f80,0xbec40000,0x3f6dbf80,
0x3f6dbf35,0xbec43f35,0xbf6d3f35,0x3ec4bf35,0xbe950000,0x3f75bf80,0xbef13f35,0xbf623f35,0xbf463f0e,0x3f22bf55,0x3dc93e48,0xbf7f3f7b,
0xbf7f3f6d,0x3dc9bec4,0x3f22bec4,0xbf463f6d,0xbf623f7b,0xbef13e48,0x3f75bf55,0xbe953f0e,0x3f7bbf80,0x3e480000,0xbe480000,0x3f7bbf80,
0x3f55bf6d,0x3f0ebec4,0xbf0e3ec4,0x3f55bf6d,0x3f0ebf35,0x3f55bf35,0xbf553f35,0x3f0ebf35,0x3e48bec4,0x3f7bbf6d,0xbf7b3f6d,0x3e48bec4,
0x3dc90000,0xbf7f3f80,0x3f46bf35,0xbf223f35,0x3e95be48,0xbf753f7b,0x3f62bf55,0xbef13f0e,0x3ef1bec4,0xbf623f6d,0x3f75bf6d,0xbe953ec4,
0x3f22bf0e,0xbf463f55,0x3f7fbf7b,0xbdc93e48,0x3f803f80,0xbf803f80,0x3f803f80,0xbf803f80,0x3f803f80,0xbf803f80,0x3f803f80,0xbf803f80,
0x3f803f80,0xbf803f80,0x3f803f80,0xbf803f80,0x3f803f80,0xbf803f80,0x3f803f80,0xbf803f80,0xbf7fbf80,0x3dc90000,0xbf22bf35,0x3f463f35,
0xbf75bf7b,0x3e953e48,0xbef1bf0e,0x3f623f55,0xbf62bf6d,0x3ef13ec4,0xbe95bec4,0x3f753f6d,0xbf46bf55,0x3f223f0e,0xbdc9be48,0x3f7f3f7b,
0x3f7b3f80,0xbe480000,0xbe480000,0xbf7bbf80,0x3f553f6d,0xbf0ebec4,0xbf0ebec4,0xbf55bf6d,0x3f0e3f35,0xbf55bf35,0xbf55bf35,0xbf0ebf35,
0x3e483ec4,0xbf7bbf6d,0xbf7bbf6d,0xbe48bec4,0xbf75bf80,0x3e950000,0x3f623f35,0x3ef13f35,0xbf22bf55,0x3f463f0e,0x3f7f3f7b,0xbdc93e48,
0xbdc9bec4,0x3f7f3f6d,0x3f463f6d,0xbf22bec4,0x3ef13e48,0x3f623f7b,0x3e953f0e,0xbf75bf55,0x3f6d3f80,0xbec40000,0xbf6dbf80,0x3ec40000,
0x3ec43f35,0xbf6dbf35,0xbec4bf35,0x3f6d3f35,0xbec40000,0xbf6dbf80,0x3ec40000,0x3f6d3f80,0xbf6dbf35,0xbec4bf35,0x3f6d3f35,0x3ec43f35,
0xbf62bf80,0x3ef10000,0x3e953f35,0xbf75bf35,0xbdc9bf0e,0x3f7f3f55,0xbf22be48,0xbf46bf7b,0x3f463ec4,0x3f223f6d,0xbf7fbf6d,0x3dc9bec4,
0x3f753f7b,0xbe953e48,0xbef1bf55,0x3f623f0e,0x3f553f80,0xbf0e0000,0x3f0e0000,0x3f553f80,0xbe483ec4,0xbf7bbf6d,0x3f7b3f6d,0xbe483ec4,
0xbf7bbf35,0xbe48bf35,0x3e483f35,0xbf7bbf35,0xbf0ebf6d,0x3f553ec4,0xbf55bec4,0xbf0ebf6d,0xbf46bf80,0x3f220000,0xbf7fbf35,0xbdc9bf35,
0x3ef1be48,0x3f623f7b,0xbe95bf55,0x3f753f0e,0x3f753f6d,0xbe953ec4,0x3f623ec4,0x3ef13f6d,0xbdc93f0e,0xbf7fbf55,0x3f223f7b,0xbf46be48,
0x3f353f80,0xbf350000,0x3f353f80,0xbf350000,0xbf350000,0xbf35bf80,0xbf350000,0xbf35bf80,0xbf35bf80,0x3f350000,0xbf35bf80,0x3f350000,
0x3f350000,0x3f353f80,0x3f350000,0x3f353f80,0xbf22bf80,0x3f460000,0x3dc9bf35,0x3f7f3f35,0x3f623e48,0x3ef13f7b,0x3f753f55,0xbe953f0e,
0x3e953f6d,0xbf75bec4,0xbef13ec4,0xbf62bf6d,0xbf7fbf0e,0xbdc9bf55,0xbf46bf7b,0x3f22be48,0x3f0e3f80,0xbf550000,0xbf550000,0xbf0ebf80,
0xbf7bbec4,0xbe48bf6d,0xbe48bf6d,0x3f7b3ec4,0x3e48bf35,0x3f7b3f35,0x3f7b3f35,0xbe483f35,0x3f553f6d,0xbf0e3ec4,0xbf0e3ec4,0xbf55bf6d,
0xbef1bf80,0x3f620000,0x3f753f35,0xbe953f35,0x3f7f3f0e,0xbdc93f55,0xbf463e48,0xbf22bf7b,0xbf223ec4,0xbf46bf6d,0xbdc9bf6d,0x3f7f3ec4,
0xbe95bf7b,0x3f753e48,0x3f623f55,0xbef13f0e,0x3ec43f80,0xbf6d0000,0xbec4bf80,0x3f6d0000,0xbf6dbf35,0x3ec4bf35,0x3f6d3f35,0xbec43f35,
0x3f6d0000,0x3ec43f80,0xbf6d0000,0xbec4bf80,0xbec43f35,0xbf6dbf35,0x3ec4bf35,0x3f6d3f35,0xbe95bf80,0x3f750000,0xbef13f35,0xbf62bf35,
0x3f463f55,0xbf223f0e,0xbdc9bf7b,0x3f7f3e48,0xbf7fbec4,0x3dc9bf6d,0x3f223f6d,0xbf463ec4,0x3f62be48,0x3ef13f7b,0xbf75bf0e,0x3e95bf55,
0x3e483f80,0xbf7b0000,0x3f7b0000,0x3e483f80,0xbf0ebf6d,0x3f55bec4,0xbf553ec4,0xbf0ebf6d,0x3f553f35,0xbf0e3f35,0x3f0ebf35,0x3f553f35,
0xbf7bbec4,0x3e48bf6d,0xbe483f6d,0xbf7bbec4,0xbdc9bf80,0x3f7f0000,0xbf46bf35,0x3f22bf35,0x3e953f7b,0xbf753e48,0x3f623f0e,0xbef13f55,
0xbef1bf6d,0x3f62bec4,0xbf75bec4,0x3e95bf6d,0x3f223f55,0xbf463f0e,0x3f7f3e48,0xbdc93f7b,0x3f80,0xbf800000,0x3f80,0xbf800000,
0xbf80,0x3f800000,0xbf80,0x3f800000,0x3f80,0xbf800000,0x3f80,0xbf800000,0xbf80,0x3f800000,0xbf80,0x3f800000,
0x3dc9bf80,0x3f7f0000,0x3f46bf35,0x3f223f35,0xbe953f7b,0xbf75be48,0xbf623f0e,0xbef1bf55,0x3ef1bf6d,0x3f623ec4,0x3f75bec4,0x3e953f6d,
0xbf223f55,0xbf46bf0e,0xbf7f3e48,0xbdc9bf7b,0xbe483f80,0xbf7b0000,0xbf7b0000,0x3e48bf80,0x3f0ebf6d,0x3f553ec4,0x3f553ec4,0xbf0e3f6d,
0xbf553f35,0xbf0ebf35,0xbf0ebf35,0x3f55bf35,0x3f7bbec4,0x3e483f6d,0x3e483f6d,0xbf7b3ec4,0x3e95bf80,0x3f750000,0x3ef13f35,0xbf623f35,
0xbf463f55,0xbf22bf0e,0x3dc9bf7b,0x3f7fbe48,0x3f7fbec4,0x3dc93f6d,0xbf223f6d,0xbf46bec4,0xbf62be48,0x3ef1bf7b,0x3f75bf0e,0x3e953f55,
0xbec43f80,0xbf6d0000,0x3ec4bf80,0x3f6d0000,0x3f6dbf35,0x3ec43f35,0xbf6d3f35,0xbec4bf35,0xbf6d0000,0x3ec4bf80,0x3f6d0000,0xbec43f80,
0x3ec43f35,0xbf6d3f35,0xbec4bf35,0x3f6dbf35,0x3ef1bf80,0x3f620000,0xbf753f35,0xbe95bf35,0xbf7f3f0e,0xbdc9bf55,0x3f463e48,0xbf223f7b,
0x3f223ec4,0xbf463f6d,0x3dc9bf6d,0x3f7fbec4,0x3e95bf7b,0x3f75be48,0xbf623f55,0xbef1bf0e,0xbf0e3f80,0xbf550000,0x3f550000,0xbf0e3f80,
0x3f7bbec4,0xbe483f6d,0x3e48bf6d,0x3f7bbec4,0xbe48bf35,0x3f7bbf35,0xbf7b3f35,0xbe48bf35,0xbf553f6d,0xbf0ebec4,0x3f0e3ec4,0xbf553f6d,
0x3f22bf80,0x3f460000,0xbdc9bf35,0x3f7fbf35,0xbf623e48,0x3ef1bf7b,0xbf753f55,0xbe95bf0e,0xbe953f6d,0xbf753ec4,0x3ef13ec4,0xbf623f6d,
0x3f7fbf0e,0xbdc93f55,0x3f46bf7b,0x3f223e48,0xbf353f80,0xbf350000,0xbf353f80,0xbf350000,0x3f350000,0xbf353f80,0x3f350000,0xbf353f80,
0x3f35bf80,0x3f350000,0x3f35bf80,0x3f350000,0xbf350000,0x3f35bf80,0xbf350000,0x3f35bf80,0x3f46bf80,0x3f220000,0x3f7fbf35,0xbdc93f35,
0xbef1be48,0x3f62bf7b,0x3e95bf55,0x3f75bf0e,0xbf753f6d,0xbe95bec4,0xbf623ec4,0x3ef1bf6d,0x3dc93f0e,0xbf7f3f55,0xbf223f7b,0xbf463e48,
0xbf553f80,0xbf0e0000,0xbf0e0000,0x3f55bf80,0x3e483ec4,0xbf7b3f6d,0xbf7b3f6d,0xbe48bec4,0x3f7bbf35,0xbe483f35,0xbe483f35,0xbf7b3f35,
0x3f0ebf6d,0x3f55bec4,0x3f55bec4,0xbf0e3f6d,0x3f62bf80,0x3ef10000,0xbe953f35,0xbf753f35,0x3dc9bf0e,0x3f7fbf55,0x3f22be48,0xbf463f7b,
0xbf463ec4,0x3f22bf6d,0x3f7fbf6d,0x3dc93ec4,0xbf753f7b,0xbe95be48,0x3ef1bf55,0x3f62bf0e,0xbf6d3f80,0xbec40000,0x3f6dbf80,0x3ec40000,
0xbec43f35,0xbf6d3f35,0x3ec4bf35,0x3f6dbf35,0x3ec40000,0xbf6d3f80,0xbec40000,0x3f6dbf80,0x3f6dbf35,0xbec43f35,0xbf6d3f35,0x3ec4bf35,
0x3f75bf80,0x3e950000,0xbf623f35,0x3ef1bf35,0x3f22bf55,0x3f46bf0e,0xbf7f3f7b,0xbdc9be48,0x3dc9bec4,0x3f7fbf6d,0xbf463f6d,0xbf223ec4,
0xbef13e48,0x3f62bf7b,0xbe953f0e,0xbf753f55,0xbf7b3f80,0xbe480000,0x3e480000,0xbf7b3f80,0xbf553f6d,0xbf0e3ec4,0x3f0ebec4,0xbf553f6d,
0xbf0e3f35,0xbf553f35,0x3f55bf35,0xbf0e3f35,0xbe483ec4,0xbf7b3f6d,0x3f7bbf6d,0xbe483ec4,0x3f7fbf80,0x3dc90000,0x3f22bf35,0x3f46bf35,
0x3f75bf7b,0x3e95be48,0x3ef1bf0e,0x3f62bf55,0x3f62bf6d,0x3ef1bec4,0x3e95bec4,0x3f75bf6d,0x3f46bf55,0x3f22bf0e,0x3dc9be48,0x3f7fbf7b,
0x3f803f80,0xbf803f80,0x3f803f80,0xbf803f80,0x3f803f80,0xbf803f80,0x3f803f80,0xbf803f80,0x3f803f80,0xbf803f80,0x3f803f80,0xbf803f80,
0x3f803f80,0xbf803f80,0x3f803f80,0xbf803f80,0x3dc90000,0x3f7f3f80,0x3f463f35,0x3f223f35,0x3e953e48,0x3f753f7b,0x3f623f55,0x3ef13f0e,
0x3ef13ec4,0x3f623f6d,0x3f753f6d,0x3e953ec4,0x3f223f0e,0x3f463f55,0x3f7f3f7b,0x3dc93e48,0xbf7bbf80,0x3e480000,0x3e480000,0x3f7b3f80,
0xbf55bf6d,0x3f0e3ec4,0x3f0e3ec4,0x3f553f6d,0xbf0ebf35,0x3f553f35,0x3f553f35,0x3f0e3f35,0xbe48bec4,0x3f7b3f6d,0x3f7b3f6d,0x3e483ec4,
0xbe950000,0xbf75bf80,0xbef1bf35,0x3f623f35,0xbf46bf0e,0xbf22bf55,0x3dc9be48,0x3f7f3f7b,0xbf7fbf6d,0xbdc9bec4,0x3f223ec4,0x3f463f6d,
0xbf62bf7b,0x3ef13e48,0x3f753f55,0x3e953f0e,0x3f6d3f80,0xbec40000,0xbf6dbf80,0x3ec40000,0x3ec43f35,0xbf6dbf35,0xbec4bf35,0x3f6d3f35,
0xbec40000,0xbf6dbf80,0x3ec40000,0x3f6d3f80,0xbf6dbf35,0xbec4bf35,0x3f6d3f35,0x3ec43f35,0x3ef10000,0x3f623f80,0xbf75bf35,0xbe95bf35,
0x3f7f3f55,0x3dc93f0e,0xbf46bf7b,0x3f223e48,0x3f223f6d,0xbf46bec4,0x3dc9bec4,0x3f7f3f6d,0xbe953e48,0xbf75bf7b,0x3f623f0e,0x3ef13f55,
0xbf55bf80,0x3f0e0000,0xbf0e0000,0xbf55bf80,0x3e48bec4,0x3f7b3f6d,0xbf7bbf6d,0x3e48bec4,0x3f7b3f35,0x3e483f35,0xbe48bf35,0x3f7b3f35,
0x3f0e3f6d,0xbf55bec4,0x3f553ec4,0x3f0e3f6d,0xbf220000,0xbf46bf80,0x3dc93f35,0xbf7fbf35,0xbf62bf7b,0x3ef1be48,0xbf75bf0e,0xbe95bf55,
0x3e95bec4,0x3f753f6d,0xbef1bf6d,0x3f623ec4,0x3f7f3f55,0xbdc93f0e,0x3f463e48,0x3f223f7b,0x3f353f80,0xbf350000,0x3f353f80,0xbf350000,
0xbf350000,0xbf35bf80,0xbf350000,0xbf35bf80,0xbf35bf80,0x3f350000,0xbf35bf80,0x3f350000,0x3f350000,0x3f353f80,0x3f350000,0x3f353f80,
0x3f460000,0x3f223f80,0x3f7f3f35,0xbdc93f35,0x3ef13f7b,0xbf62be48,0xbe953f0e,0xbf75bf55,0xbf75bec4,0xbe95bf6d,0xbf62bf6d,0x3ef1bec4,
0xbdc9bf55,0x3f7f3f0e,0x3f22be48,0x3f463f7b,0xbf0ebf80,0x3f550000,0x3f550000,0x3f0e3f80,0x3f7b3ec4,0x3e483f6d,0x3e483f6d,0xbf7bbec4,
0xbe483f35,0xbf7bbf35,0xbf7bbf35,0x3e48bf35,0xbf55bf6d,0x3f0ebec4,0x3f0ebec4,0x3f553f6d,0xbf620000,0xbef1bf80,0x3e95bf35,0x3f753f35,
0x3dc9bf55,0x3f7f3f0e,0x3f223f7b,0xbf463e48,0x3f463f6d,0xbf223ec4,0xbf7fbec4,0xbdc9bf6d,0xbf75be48,0xbe95bf7b,0x3ef1bf0e,0x3f623f55,
0x3ec43f80,0xbf6d0000,0xbec4bf80,0x3f6d0000,0xbf6dbf35,0x3ec4bf35,0x3f6d3f35,0xbec43f35,0x3f6d0000,0x3ec43f80,0xbf6d0000,0xbec4bf80,
0xbec43f35,0xbf6dbf35,0x3ec4bf35,0x3f6d3f35,0x3f750000,0x3e953f80,0xbf62bf35,0x3ef1bf35,0xbf223f0e,0xbf46bf55,0x3f7f3e48,0x3dc93f7b,
0x3dc9bf6d,0x3f7f3ec4,0xbf463ec4,0xbf22bf6d,0x3ef13f7b,0xbf623e48,0x3e95bf55,0x3f753f0e,0xbe48bf80,0x3f7b0000,0xbf7b0000,0xbe48bf80,
0x3f0e3f6d,0xbf553ec4,0x3f55bec4,0x3f0e3f6d,0xbf55bf35,0x3f0ebf35,0xbf0e3f35,0xbf55bf35,0x3f7b3ec4,0xbe483f6d,0x3e48bf6d,0x3f7b3ec4,
0xbf7f0000,0xbdc9bf80,0xbf223f35,0xbf46bf35,0x3f75be48,0x3e953f7b,0x3ef1bf55,0x3f623f0e,0xbf623ec4,0xbef1bf6d,0xbe953f6d,0xbf75bec4,
0x3f46bf0e,0x3f223f55,0x3dc9bf7b,0x3f7f3e48,0x3f80,0xbf800000,0x3f80,0xbf800000,0xbf80,0x3f800000,0xbf80,0x3f800000,
0x3f80,0xbf800000,0x3f80,0xbf800000,0xbf80,0x3f800000,0xbf80,0x3f800000,0x3f7f0000,0xbdc93f80,0x3f223f35,0xbf463f35,
0xbf75be48,0x3e95bf7b,0xbef1bf55,0x3f62bf0e,0x3f623ec4,0xbef13f6d,0x3e953f6d,0xbf753ec4,0xbf46bf0e,0x3f22bf55,0xbdc9bf7b,0x3f7fbe48,
0x3e48bf80,0x3f7b0000,0x3f7b0000,0xbe483f80,0xbf0e3f6d,0xbf55bec4,0xbf55bec4,0x3f0ebf6d,0x3f55bf35,0x3f0e3f35,0x3f0e3f35,0xbf553f35,
0xbf7b3ec4,0xbe48bf6d,0xbe48bf6d,0x3f7bbec4,0xbf750000,0x3e95bf80,0x3f62bf35,0x3ef13f35,0x3f223f0e,0xbf463f55,0xbf7f3e48,0x3dc9bf7b,
0xbdc9bf6d,0x3f7fbec4,0x3f463ec4,0xbf223f6d,0xbef13f7b,0xbf62be48,0xbe95bf55,0x3f75bf0e,0xbec43f80,0xbf6d0000,0x3ec4bf80,0x3f6d0000,
0x3f6dbf35,0x3ec43f35,0xbf6d3f35,0xbec4bf35,0xbf6d0000,0x3ec4bf80,0x3f6d0000,0xbec43f80,0x3ec43f35,0xbf6d3f35,0xbec4bf35,0x3f6dbf35,
0x3f620000,0xbef13f80,0xbe95bf35,0x3f75bf35,0xbdc9bf55,0x3f7fbf0e,0xbf223f7b,0xbf46be48,0xbf463f6d,0xbf22bec4,0x3f7fbec4,0xbdc93f6d,
0x3f75be48,0xbe953f7b,0xbef1bf0e,0x3f62bf55,0x3f0ebf80,0x3f550000,0xbf550000,0x3f0ebf80,0xbf7b3ec4,0x3e48bf6d,0xbe483f6d,0xbf7b3ec4,
0x3e483f35,0xbf7b3f35,0x3f7bbf35,0x3e483f35,0x3f55bf6d,0x3f0e3ec4,0xbf0ebec4,0x3f55bf6d,0xbf460000,0x3f22bf80,0xbf7f3f35,0xbdc9bf35,
0xbef13f7b,0xbf623e48,0x3e953f0e,0xbf753f55,0x3f75bec4,0xbe953f6d,0x3f62bf6d,0x3ef13ec4,0x3dc9bf55,0x3f7fbf0e,0xbf22be48,0x3f46bf7b,
0xbf353f80,0xbf350000,0xbf353f80,0xbf350000,0x3f350000,0xbf353f80,0x3f350000,0xbf353f80,0x3f35bf80,0x3f350000,0x3f35bf80,0x3f350000,
0xbf350000,0x3f35bf80,0xbf350000,0x3f35bf80,0x3f220000,0xbf463f80,0xbdc93f35,0xbf7f3f35,0x3f62bf7b,0x3ef13e48,0x3f75bf0e,0xbe953f55,
0xbe95bec4,0x3f75bf6d,0x3ef1bf6d,0x3f62bec4,0xbf7f3f55,0xbdc9bf0e,0xbf463e48,0x3f22bf7b,0x3f55bf80,0x3f0e0000,0x3f0e0000,0xbf553f80,
0xbe48bec4,0x3f7bbf6d,0x3f7bbf6d,0x3e483ec4,0xbf7b3f35,0x3e48bf35,0x3e48bf35,0x3f7bbf35,0xbf0e3f6d,0xbf553ec4,0xbf553ec4,0x3f0ebf6d,
0xbef10000,0x3f62bf80,0x3f75bf35,0xbe953f35,0xbf7f3f55,0x3dc9bf0e,0x3f46bf7b,0x3f22be48,0xbf223f6d,0xbf463ec4,0xbdc9bec4,0x3f7fbf6d,
0x3e953e48,0xbf753f7b,0xbf623f0e,0x3ef1bf55,0xbf6d3f80,0xbec40000,0x3f6dbf80,0x3ec40000,0xbec43f35,0xbf6d3f35,0x3ec4bf35,0x3f6dbf35,
0x3ec40000,0xbf6d3f80,0xbec40000,0x3f6dbf80,0x3f6dbf35,0xbec43f35,0xbf6d3f35,0x3ec4bf35,0x3e950000,0xbf753f80,0x3ef1bf35,0x3f62bf35,
0x3f46bf0e,0xbf223f55,0xbdc9be48,0x3f7fbf7b,0x3f7fbf6d,0xbdc93ec4,0xbf223ec4,0x3f46bf6d,0x3f62bf7b,0x3ef1be48,0xbf753f55,0x3e95bf0e,
0x3f7bbf80,0x3e480000,0xbe480000,0x3f7bbf80,0x3f55bf6d,0x3f0ebec4,0xbf0e3ec4,0x3f55bf6d,0x3f0ebf35,0x3f55bf35,0xbf553f35,0x3f0ebf35,
0x3e48bec4,0x3f7bbf6d,0xbf7b3f6d,0x3e48bec4,0xbdc90000,0x3f7fbf80,0xbf463f35,0x3f22bf35,0xbe953e48,0x3f75bf7b,0xbf623f55,0x3ef1bf0e,
0xbef13ec4,0x3f62bf6d,0xbf753f6d,0x3e95bec4,0xbf223f0e,0x3f46bf55,0xbf7f3f7b,0x3dc9be48,0x40003f80,0xc0003f80,0x3f80,0x3f80,
0x40004000,0xc0004000,0x0,0x0,0x40004000,0xc0004000,0x0,0x0,0x40004000,0xc0004000,0x0,0x0,
0x3fed3f80,0xbfed3f80,0xbf44bf80,0x3f44bf80,0x3f443fb5,0xbf443fb5,0xbfedbfb5,0x3fedbfb5,0xbf440000,0x3f440000,0xbfedc000,0x3fedc000,
0xbfedbfb5,0x3fedbfb5,0xbf44bfb5,0x3f44bfb5,0x3fb53f80,0xbfb53f80,0xbfb53f80,0x3fb53f80,0xbfb50000,0x3fb50000,0xbfb5c000,0x3fb5c000,
0xbfb5c000,0x3fb5c000,0x3fb50000,0xbfb50000,0x3fb50000,0xbfb50000,0x3fb54000,0xbfb54000,0x3f443f80,0xbf443f80,0xbfedbf80,0x3fedbf80,
0xbfedbfb5,0x3fedbfb5,0x3f44bfb5,0xbf44bfb5,0x3fed0000,0xbfed0000,0x3f444000,0xbf444000,0xbf443fb5,0x3f443fb5,0xbfedbfb5,0x3fedbfb5,
0x3f80,0x3f80,0xc0003f80,0x40003f80,0xc000,0xc000,0x40000000,0xc0000000,0x4000,0x4000,0xc0000000,0x40000000,
0xc000,0xc000,0x40000000,0xc0000000,0xbf443f80,0x3f443f80,0xbfedbf80,0x3fedbf80,0x3fedbfb5,0xbfedbfb5,0x3f443fb5,0xbf443fb5,
0xbfed0000,0x3fed0000,0x3f44c000,0xbf44c000,0x3f443fb5,0xbf443fb5,0xbfed3fb5,0x3fed3fb5,0xbfb53f80,0x3fb53f80,0xbfb53f80,0x3fb53f80,
0x3fb50000,0xbfb50000,0xbfb54000,0x3fb54000,0x3fb5c000,0xbfb5c000,0x3fb50000,0xbfb50000,0xbfb50000,0x3fb50000,0x3fb5c000,0xbfb5c000,
0xbfed3f80,0x3fed3f80,0xbf44bf80,0x3f44bf80,0xbf443fb5,0x3f443fb5,0xbfed3fb5,0x3fed3fb5,0x3f440000,0xbf440000,0xbfed4000,0x3fed4000,
0x3fedbfb5,0xbfedbfb5,0xbf443fb5,0x3f443fb5,0x40003f80,0xc0003f80,0x3f80,0x3f80,0x40004000,0xc0004000,0x0,0x0,
0x40004000,0xc0004000,0x0,0x0,0x40004000,0xc0004000,0x0,0x0,0x3fed3f80,0xbfed3f80,0xbf44bf80,0x3f44bf80,
0x3f443fb5,0xbf443fb5,0xbfedbfb5,0x3fedbfb5,0xbf440000,0x3f440000,0xbfedc000,0x3fedc000,0xbfedbfb5,0x3fedbfb5,0xbf44bfb5,0x3f44bfb5,
0x3fb53f80,0xbfb53f80,0xbfb53f80,0x3fb53f80,0xbfb50000,0x3fb50000,0xbfb5c000,0x3fb5c000,0xbfb5c000,0x3fb5c000,0x3fb50000,0xbfb50000,
0x3fb50000,0xbfb50000,0x3fb54000,0xbfb54000,0x3f443f80,0xbf443f80,0xbfedbf80,0x3fedbf80,0xbfedbfb5,0x3fedbfb5,0x3f44bfb5,0xbf44bfb5,
0x3fed0000,0xbfed0000,0x3f444000,0xbf444000,0xbf443fb5,0x3f443fb5,0xbfedbfb5,0x3fedbfb5,0x3f80,0x3f80,0xc0003f80,0x40003f80,
0xc000,0xc000,0x40000000,0xc0000000,0x4000,0x4000,0xc0000000,0x40000000,0xc000,0xc000,0x40000000,0xc0000000,
0xbf443f80,0x3f443f80,0xbfedbf80,0x3fedbf80,0x3fedbfb5,0xbfedbfb5,0x3f443fb5,0xbf443fb5,0xbfed0000,0x3fed0000,0x3f44c000,0xbf44c000,
0x3f443fb5,0xbf443fb5,0xbfed3fb5,0x3fed3fb5,0xbfb53f80,0x3fb53f80,0xbfb53f80,0x3fb53f80,0x3fb50000,0xbfb50000,0xbfb54000,0x3fb54000,
0x3fb5c000,0xbfb5c000,0x3fb50000,0xbfb50000,0xbfb50000,0x3fb50000,0x3fb5c000,0xbfb5c000,0xbfed3f80,0x3fed3f80,0xbf44bf80,0x3f44bf80,
0xbf443fb5,0x3f443fb5,0xbfed3fb5,0x3fed3fb5,0x3f440000,0xbf440000,0xbfed4000,0x3fed4000,0x3fedbfb5,0xbfedbfb5,0xbf443fb5,0x3f443fb5,
0x40003f80,0xc0003f80,0x3f80,0x3f80,0x40004000,0xc0004000,0x0,0x0,0x40004000,0xc0004000,0x0,0x0,
0x40004000,0xc0004000,0x0,0x0,0x3fed3f80,0xbfed3f80,0xbf44bf80,0x3f44bf80,0x3f443fb5,0xbf443fb5,0xbfedbfb5,0x3fedbfb5,
0xbf440000,0x3f440000,0xbfedc000,0x3fedc000,0xbfedbfb5,0x3fedbfb5,0xbf44bfb5,0x3f44bfb5,0x3fb53f80,0xbfb53f80,0xbfb53f80,0x3fb53f80,
0xbfb50000,0x3fb50000,0xbfb5c000,0x3fb5c000,0xbfb5c000,0x3fb5c000,0x3fb50000,0xbfb50000,0x3fb50000,0xbfb50000,0x3fb54000,0xbfb54000,
0x3f443f80,0xbf443f80,0xbfedbf80,0x3fedbf80,0xbfedbfb5,0x3fedbfb5,0x3f44bfb5,0xbf44bfb5,0x3fed0000,0xbfed0000,0x3f444000,0xbf444000,
0xbf443fb5,0x3f443fb5,0xbfedbfb5,0x3fedbfb5,0x3f80,0x3f80,0xc0003f80,0x40003f80,0xc000,0xc000,0x40000000,0xc0000000,
0x4000,0x4000,0xc0000000,0x40000000,0xc000,0xc000,0x40000000,0xc0000000,0xbf443f80,0x3f443f80,0xbfedbf80,0x3fedbf80,
0x3fedbfb5,0xbfedbfb5,0x3f443fb5,0xbf443fb5,0xbfed0000,0x3fed0000,0x3f44c000,0xbf44c000,0x3f443fb5,0xbf443fb5,0xbfed3fb5,0x3fed3fb5,
0xbfb53f80,0x3fb53f80,0xbfb53f80,0x3fb53f80,0x3fb50000,0xbfb50000,0xbfb54000,0x3fb54000,0x3fb5c000,0xbfb5c000,0x3fb50000,0xbfb50000,
0xbfb50000,0x3fb50000,0x3fb5c000,0xbfb5c000,0xbfed3f80,0x3fed3f80,0xbf44bf80,0x3f44bf80,0xbf443fb5,0x3f443fb5,0xbfed3fb5,0x3fed3fb5,
0x3f440000,0xbf440000,0xbfed4000,0x3fed4000,0x3fedbfb5,0xbfedbfb5,0xbf443fb5,0x3f443fb5,0x40003f80,0xc0003f80,0x3f80,0x3f80,
0x40004000,0xc0004000,0x0,0x0,0x40004000,0xc0004000,0x0,0x0,0x40004000,0xc0004000,0x0,0x0,
0x3fed3f80,0xbfed3f80,0xbf44bf80,0x3f44bf80,0x3f443fb5,0xbf443fb5,0xbfedbfb5,0x3fedbfb5,0xbf440000,0x3f440000,0xbfedc000,0x3fedc000,
0xbfedbfb5,0x3fedbfb5,0xbf44bfb5,0x3f44bfb5,0x3fb53f80,0xbfb53f80,0xbfb53f80,0x3fb53f80,0xbfb50000,0x3fb50000,0xbfb5c000,0x3fb5c000,
0xbfb5c000,0x3fb5c000,0x3fb50000,0xbfb50000,0x3fb50000,0xbfb50000,0x3fb54000,0xbfb54000,0x3f443f80,0xbf443f80,0xbfedbf80,0x3fedbf80,
0xbfedbfb5,0x3fedbfb5,0x3f44bfb5,0xbf44bfb5,0x3fed0000,0xbfed0000,0x3f444000,0xbf444000,0xbf443fb5,0x3f443fb5,0xbfedbfb5,0x3fedbfb5,
0x3f80,0x3f80,0xc0003f80,0x40003f80,0xc000,0xc000,0x40000000,0xc0000000,0x4000,0x4000,0xc0000000,0x40000000,
0xc000,0xc000,0x40000000,0xc0000000,0xbf443f80,0x3f443f80,0xbfedbf80,0x3fedbf80,0x3fedbfb5,0xbfedbfb5,0x3f443fb5,0xbf443fb5,
0xbfed0000,0x3fed0000,0x3f44c000,0xbf44c000,0x3f443fb5,0xbf443fb5,0xbfed3fb5,0x3fed3fb5,0xbfb53f80,0x3fb53f80,0xbfb53f80,0x3fb53f80,
0x3fb50000,0xbfb50000,0xbfb54000,0x3fb54000,0x3fb5c000,0xbfb5c000,0x3fb50000,0xbfb50000,0xbfb50000,0x3fb50000,0x3fb5c000,0xbfb5c000,
0xbfed3f80,0x3fed3f80,0xbf44bf80,0x3f44bf80,0xbf443fb5,0x3f443fb5,0xbfed3fb5,0x3fed3fb5,0x3f440000,0xbf440000,0xbfed4000,0x3fed4000,
0x3fedbfb5,0xbfedbfb5,0xbf443fb5,0x3f443fb5,0x40004000,0xbfb53fb5,0x0,0x3fb5bfb5,0x40004000,0xbfb53fb5,0x0,0x3fb5bfb5,
0x40004000,0xbfb53fb5,0x0,0x3fb5bfb5,0x40004000,0xbfb53fb5,0x0,0x3fb5bfb5,0x3fe23fff,0xbf153fa2,0xbf71be49,0x3ff5bfc6,
0x3f153fa2,0x3f71be49,0xbff5bfc6,0x3fe2bfff,0xbf71be49,0x3ff5bfc6,0xbfe2bfff,0x3f15bfa2,0xbff5bfc6,0x3fe2bfff,0xbf15bfa2,0xbf713e49,
0x3f8e3ffb,0x3ec83f8e,0xbfd5bec8,0x3ffbbfd5,0xbfd5bec8,0x3ffbbfd5,0xbf8ebffb,0xbec8bf8e,0xbf8ebffb,0xbec8bf8e,0x3fd53ec8,0xbffb3fd5,
0x3fd53ec8,0xbffb3fd5,0x3f8e3ffb,0x3ec83f8e,0x3e493ff5,0x3fa23f71,0xbfffbf15,0x3fc6bfe2,0xbfc6bfe2,0x3e49bff5,0x3fa2bf71,0xbfff3f15,
0x3fff3f15,0xbfc63fe2,0x3e493ff5,0x3fa23f71,0xbfa23f71,0x3fffbf15,0xbfc6bfe2,0x3e49bff5,0xbf443fed,0x3fed3f44,0xbfedbf44,0x3f44bfed,
0x3f44bfed,0xbfedbf44,0x3fed3f44,0xbf443fed,0xbf443fed,0x3fed3f44,0xbfedbf44,0x3f44bfed,0x3f44bfed,0xbfedbf44,0x3fed3f44,0xbf443fed,
0xbfc63fe2,0x3fff3f15,0xbfa2bf71,0xbe49bff5,0x3fffbf15,0xbfa23f71,0xbe493ff5,0x3fc63fe2,0xbfa2bf71,0xbe49bff5,0x3fc6bfe2,0xbfffbf15,
0xbe493ff5,0x3fc63fe2,0xbfff3f15,0x3fa2bf71,0xbffb3fd5,0x3fd53ec8,0xbec8bf8e,0xbf8ebffb,0x3ec83f8e,0x3f8e3ffb,0xbffb3fd5,0x3fd53ec8,
0x3ffbbfd5,0xbfd5bec8,0x3ec83f8e,0x3f8e3ffb,0xbec8bf8e,0xbf8ebffb,0x3ffbbfd5,0xbfd5bec8,0xbff53fc6,0x3f713e49,0x3f15bfa2,0xbfe2bfff,
0xbfe23fff,0x3ff53fc6,0xbf713e49,0xbf15bfa2,0xbf153fa2,0x3fe23fff,0xbff53fc6,0x3f713e49,0x3f71be49,0x3f153fa2,0xbfe23fff,0x3ff53fc6,
0x0,0x3fb5bfb5,0xc000c000,0x3fb5bfb5,0x0,0x3fb5bfb5,0xc000c000,0x3fb5bfb5,0x0,0x3fb5bfb5,0xc000c000,0x3fb5bfb5,
0x0,0x3fb5bfb5,0xc000c000,0x3fb5bfb5,0xbf71be49,0x3ff5bfc6,0xbfe2bfff,0x3f15bfa2,0xbff5bfc6,0x3fe2bfff,0xbf15bfa2,0xbf713e49,
0xbfe2bfff,0x3f15bfa2,0x3f713e49,0xbff53fc6,0xbf15bfa2,0xbf713e49,0x3ff53fc6,0xbfe23fff,0xbfd5bec8,0x3ffbbfd5,0xbf8ebffb,0xbec8bf8e,
0xbf8ebffb,0xbec8bf8e,0x3fd53ec8,0xbffb3fd5,0x3fd53ec8,0xbffb3fd5,0x3f8e3ffb,0x3ec83f8e,0x3f8e3ffb,0x3ec83f8e,0xbfd5bec8,0x3ffbbfd5,
0xbfffbf15,0x3fc6bfe2,0xbe49bff5,0xbfa2bf71,0x3fa2bf71,0xbfff3f15,0x3fc63fe2,0xbe493ff5,0x3e493ff5,0x3fa23f71,0xbfffbf15,0x3fc6bfe2,
0xbfc6bfe2,0x3e49bff5,0x3fa2bf71,0xbfff3f15,0xbfedbf44,0x3f44bfed,0x3f44bfed,0xbfedbf44,0x3fed3f44,0xbf443fed,0xbf443fed,0x3fed3f44,
0xbfedbf44,0x3f44bfed,0x3f44bfed,0xbfedbf44,0x3fed3f44,0xbf443fed,0xbf443fed,0x3fed3f44,0xbfa2bf71,0xbe49bff5,0x3fc6bfe2,0xbfffbf15,
0xbe493ff5,0x3fc63fe2,0xbfff3f15,0x3fa2bf71,0x3fc6bfe2,0xbfffbf15,0x3fa23f71,0x3e493ff5,0xbfff3f15,0x3fa2bf71,0x3e49bff5,0xbfc6bfe2,
0xbec8bf8e,0xbf8ebffb,0x3ffbbfd5,0xbfd5bec8,0xbffb3fd5,0x3fd53ec8,0xbec8bf8e,0xbf8ebffb,0x3ec83f8e,0x3f8e3ffb,0xbffb3fd5,0x3fd53ec8,
0x3ffbbfd5,0xbfd5bec8,0x3ec83f8e,0x3f8e3ffb,0x3f15bfa2,0xbfe2bfff,0x3ff5bfc6,0xbf71be49,0xbf713e49,0xbf15bfa2,0x3fe2bfff,0xbff5bfc6,
0xbff53fc6,0x3f713e49,0x3f15bfa2,0xbfe2bfff,0xbfe23fff,0x3ff53fc6,0xbf713e49,0xbf15bfa2,0xc000c000,0x3fb5bfb5,0x0,0xbfb53fb5,
0xc000c000,0x3fb5bfb5,0x0,0xbfb53fb5,0xc000c000,0x3fb5bfb5,0x0,0xbfb53fb5,0xc000c000,0x3fb5bfb5,0x0,0xbfb53fb5,
0xbfe2bfff,0x3f15bfa2,0x3f713e49,0xbff53fc6,0xbf15bfa2,0xbf713e49,0x3ff53fc6,0xbfe23fff,0x3f713e49,0xbff53fc6,0x3fe23fff,0xbf153fa2,
0x3ff53fc6,0xbfe23fff,0x3f153fa2,0x3f71be49,0xbf8ebffb,0xbec8bf8e,0x3fd53ec8,0xbffb3fd5,0x3fd53ec8,0xbffb3fd5,0x3f8e3ffb,0x3ec83f8e,
0x3f8e3ffb,0x3ec83f8e,0xbfd5bec8,0x3ffbbfd5,0xbfd5bec8,0x3ffbbfd5,0xbf8ebffb,0xbec8bf8e,0xbe49bff5,0xbfa2bf71,0x3fff3f15,0xbfc63fe2,
0x3fc63fe2,0xbe493ff5,0xbfa23f71,0x3fffbf15,0xbfffbf15,0x3fc6bfe2,0xbe49bff5,0xbfa2bf71,0x3fa2bf71,0xbfff3f15,0x3fc63fe2,0xbe493ff5,
0x3f44bfed,0xbfedbf44,0x3fed3f44,0xbf443fed,0xbf443fed,0x3fed3f44,0xbfedbf44,0x3f44bfed,0x3f44bfed,0xbfedbf44,0x3fed3f44,0xbf443fed,
0xbf443fed,0x3fed3f44,0xbfedbf44,0x3f44bfed,0x3fc6bfe2,0xbfffbf15,0x3fa23f71,0x3e493ff5,0xbfff3f15,0x3fa2bf71,0x3e49bff5,0xbfc6bfe2,
0x3fa23f71,0x3e493ff5,0xbfc63fe2,0x3fff3f15,0x3e49bff5,0xbfc6bfe2,0x3fffbf15,0xbfa23f71,0x3ffbbfd5,0xbfd5bec8,0x3ec83f8e,0x3f8e3ffb,
0xbec8bf8e,0xbf8ebffb,0x3ffbbfd5,0xbfd5bec8,0xbffb3fd5,0x3fd53ec8,0xbec8bf8e,0xbf8ebffb,0x3ec83f8e,0x3f8e3ffb,0xbffb3fd5,0x3fd53ec8,
0x3ff5bfc6,0xbf71be49,0xbf153fa2,0x3fe23fff,0x3fe2bfff,0xbff5bfc6,0x3f71be49,0x3f153fa2,0x3f15bfa2,0xbfe2bfff,0x3ff5bfc6,0xbf71be49,
0xbf713e49,0xbf15bfa2,0x3fe2bfff,0xbff5bfc6,0x0,0xbfb53fb5,0x40004000,0xbfb53fb5,0x0,0xbfb53fb5,0x40004000,0xbfb53fb5,
0x0,0xbfb53fb5,0x40004000,0xbfb53fb5,0x0,0xbfb53fb5,0x40004000,0xbfb53fb5,0x3f713e49,0xbff53fc6,0x3fe23fff,0xbf153fa2,
0x3ff53fc6,0xbfe23fff,0x3f153fa2,0x3f71be49,0x3fe23fff,0xbf153fa2,0xbf71be49,0x3ff5bfc6,0x3f153fa2,0x3f71be49,0xbff5bfc6,0x3fe2bfff,
0x3fd53ec8,0xbffb3fd5,0x3f8e3ffb,0x3ec83f8e,0x3f8e3ffb,0x3ec83f8e,0xbfd5bec8,0x3ffbbfd5,0xbfd5bec8,0x3ffbbfd5,0xbf8ebffb,0xbec8bf8e,
0xbf8ebffb,0xbec8bf8e,0x3fd53ec8,0xbffb3fd5,0x3fff3f15,0xbfc63fe2,0x3e493ff5,0x3fa23f71,0xbfa23f71,0x3fffbf15,0xbfc6bfe2,0x3e49bff5,
0xbe49bff5,0xbfa2bf71,0x3fff3f15,0xbfc63fe2,0x3fc63fe2,0xbe493ff5,0xbfa23f71,0x3fffbf15,0x3fed3f44,0xbf443fed,0xbf443fed,0x3fed3f44,
0xbfedbf44,0x3f44bfed,0x3f44bfed,0xbfedbf44,0x3fed3f44,0xbf443fed,0xbf443fed,0x3fed3f44,0xbfedbf44,0x3f44bfed,0x3f44bfed,0xbfedbf44,
0x3fa23f71,0x3e493ff5,0xbfc63fe2,0x3fff3f15,0x3e49bff5,0xbfc6bfe2,0x3fffbf15,0xbfa23f71,0xbfc63fe2,0x3fff3f15,0xbfa2bf71,0xbe49bff5,
0x3fffbf15,0xbfa23f71,0xbe493ff5,0x3fc63fe2,0x3ec83f8e,0x3f8e3ffb,0xbffb3fd5,0x3fd53ec8,0x3ffbbfd5,0xbfd5bec8,0x3ec83f8e,0x3f8e3ffb,
0xbec8bf8e,0xbf8ebffb,0x3ffbbfd5,0xbfd5bec8,0xbffb3fd5,0x3fd53ec8,0xbec8bf8e,0xbf8ebffb,0xbf153fa2,0x3fe23fff,0xbff53fc6,0x3f713e49,
0x3f71be49,0x3f153fa2,0xbfe23fff,0x3ff53fc6,0x3ff5bfc6,0xbf71be49,0xbf153fa2,0x3fe23fff,0x3fe2bfff,0xbff5bfc6,0x3f71be49,0x3f153fa2,
0x40004000,0x0,0x0,0x4000c000,0x40004000,0x0,0x0,0x4000c000,0x40004000,0x0,0x0,0x4000c000,
0x40004000,0x0,0x0,0x4000c000,0x3fd53ffb,0x3f8ebec8,0xbf8ebec8,0x3fd5bffb,0x3ec83f8e,0x3ffbbfd5,0xbffbbfd5,0x3ec8bf8e,
0xbf8ebec8,0x3fd5bffb,0xbfd5bffb,0xbf8e3ec8,0xbffbbfd5,0x3ec8bf8e,0xbec8bf8e,0xbffb3fd5,0x3f443fed,0x3fedbf44,0xbfedbf44,0x3f44bfed,
0xbfedbf44,0x3f44bfed,0xbf44bfed,0xbfed3f44,0xbf44bfed,0xbfed3f44,0x3fed3f44,0xbf443fed,0x3fed3f44,0xbf443fed,0x3f443fed,0x3fedbf44,
0xbec83fd5,0x3ffbbf8e,0xbffbbf8e,0xbec8bfd5,0xbf8ebffb,0xbfd5bec8,0x3fd5bec8,0xbf8e3ffb,0x3ffb3f8e,0x3ec83fd5,0xbec83fd5,0x3ffbbf8e,
0xbfd53ec8,0x3f8ebffb,0xbf8ebffb,0xbfd5bec8,0xbfb53fb5,0x3fb5bfb5,0xbfb5bfb5,0xbfb5bfb5,0x3fb5bfb5,0xbfb53fb5,0x3fb53fb5,0x3fb53fb5,
0xbfb53fb5,0x3fb5bfb5,0xbfb5bfb5,0xbfb5bfb5,0x3fb5bfb5,0xbfb53fb5,0x3fb53fb5,0x3fb53fb5,0xbffb3f8e,0x3ec8bfd5,0xbec8bfd5,0xbffbbf8e,
0x3fd53ec8,0x3f8e3ffb,0xbf8e3ffb,0x3fd5bec8,0xbec8bfd5,0xbffbbf8e,0x3ffbbf8e,0xbec83fd5,0xbf8e3ffb,0x3fd5bec8,0xbfd5bec8,0xbf8ebffb,
0xbfed3f44,0xbf44bfed,0x3f44bfed,0xbfedbf44,0xbf443fed,0x3fed3f44,0xbfed3f44,0xbf44bfed,0x3fedbf44,0x3f443fed,0xbf443fed,0x3fed3f44,
0x3f44bfed,0xbfedbf44,0x3fedbf44,0x3f443fed,0xbf8e3ec8,0xbfd5bffb,0x3fd5bffb,0xbf8ebec8,0xbffb3fd5,0xbec8bf8e,0x3ec8bf8e,0xbffbbfd5,
0xbfd53ffb,0x3f8e3ec8,0xbf8e3ec8,0xbfd5bffb,0xbec83f8e,0x3ffb3fd5,0xbffb3fd5,0xbec8bf8e,0xc000c000,0x0,0x0,0xc0004000,
0xc000c000,0x0,0x0,0xc0004000,0xc000c000,0x0,0x0,0xc0004000,0xc000c000,0x0,0x0,0xc0004000,
0xbfd5bffb,0xbf8e3ec8,0x3f8e3ec8,0xbfd53ffb,0xbec8bf8e,0xbffb3fd5,0x3ffb3fd5,0xbec83f8e,0x3f8e3ec8,0xbfd53ffb,0x3fd53ffb,0x3f8ebec8,
0x3ffb3fd5,0xbec83f8e,0x3ec83f8e,0x3ffbbfd5,0xbf44bfed,0xbfed3f44,0x3fed3f44,0xbf443fed,0x3fed3f44,0xbf443fed,0x3f443fed,0x3fedbf44,
0x3f443fed,0x3fedbf44,0xbfedbf44,0x3f44bfed,0xbfedbf44,0x3f44bfed,0xbf44bfed,0xbfed3f44,0x3ec8bfd5,0xbffb3f8e,0x3ffb3f8e,0x3ec83fd5,
0x3f8e3ffb,0x3fd53ec8,0xbfd53ec8,0x3f8ebffb,0xbffbbf8e,0xbec8bfd5,0x3ec8bfd5,0xbffb3f8e,0x3fd5bec8,0xbf8e3ffb,0x3f8e3ffb,0x3fd53ec8,
0x3fb5bfb5,0xbfb53fb5,0x3fb53fb5,0x3fb53fb5,0xbfb53fb5,0x3fb5bfb5,0xbfb5bfb5,0xbfb5bfb5,0x3fb5bfb5,0xbfb53fb5,0x3fb53fb5,0x3fb53fb5,
0xbfb53fb5,0x3fb5bfb5,0xbfb5bfb5,0xbfb5bfb5,0x3ffbbf8e,0xbec83fd5,0x3ec83fd5,0x3ffb3f8e,0xbfd5bec8,0xbf8ebffb,0x3f8ebffb,0xbfd53ec8,
0x3ec83fd5,0x3ffb3f8e,0xbffb3f8e,0x3ec8bfd5,0x3f8ebffb,0xbfd53ec8,0x3fd53ec8,0x3f8e3ffb,0x3fedbf44,0x3f443fed,0xbf443fed,0x3fed3f44,
0x3f44bfed,0xbfedbf44,0x3fedbf44,0x3f443fed,0xbfed3f44,0xbf44bfed,0x3f44bfed,0xbfedbf44,0xbf443fed,0x3fed3f44,0xbfed3f44,0xbf44bfed,
0x3f8ebec8,0x3fd53ffb,0xbfd53ffb,0x3f8e3ec8,0x3ffbbfd5,0x3ec83f8e,0xbec83f8e,0x3ffb3fd5,0x3fd5bffb,0xbf8ebec8,0x3f8ebec8,0x3fd53ffb,
0x3ec8bf8e,0xbffbbfd5,0x3ffbbfd5,0x3ec83f8e,0x40004000,0x0,0x0,0x4000c000,0x40004000,0x0,0x0,0x4000c000,
0x40004000,0x0,0x0,0x4000c000,0x40004000,0x0,0x0,0x4000c000,0x3fd53ffb,0x3f8ebec8,0xbf8ebec8,0x3fd5bffb,
0x3ec83f8e,0x3ffbbfd5,0xbffbbfd5,0x3ec8bf8e,0xbf8ebec8,0x3fd5bffb,0xbfd5bffb,0xbf8e3ec8,0xbffbbfd5,0x3ec8bf8e,0xbec8bf8e,0xbffb3fd5,
0x3f443fed,0x3fedbf44,0xbfedbf44,0x3f44bfed,0xbfedbf44,0x3f44bfed,0xbf44bfed,0xbfed3f44,0xbf44bfed,0xbfed3f44,0x3fed3f44,0xbf443fed,
0x3fed3f44,0xbf443fed,0x3f443fed,0x3fedbf44,0xbec83fd5,0x3ffbbf8e,0xbffbbf8e,0xbec8bfd5,0xbf8ebffb,0xbfd5bec8,0x3fd5bec8,0xbf8e3ffb,
0x3ffb3f8e,0x3ec83fd5,0xbec83fd5,0x3ffbbf8e,0xbfd53ec8,0x3f8ebffb,0xbf8ebffb,0xbfd5bec8,0xbfb53fb5,0x3fb5bfb5,0xbfb5bfb5,0xbfb5bfb5,
0x3fb5bfb5,0xbfb53fb5,0x3fb53fb5,0x3fb53fb5,0xbfb53fb5,0x3fb5bfb5,0xbfb5bfb5,0xbfb5bfb5,0x3fb5bfb5,0xbfb53fb5,0x3fb53fb5,0x3fb53fb5,
0xbffb3f8e,0x3ec8bfd5,0xbec8bfd5,0xbffbbf8e,0x3fd53ec8,0x3f8e3ffb,0xbf8e3ffb,0x3fd5bec8,0xbec8bfd5,0xbffbbf8e,0x3ffbbf8e,0xbec83fd5,
0xbf8e3ffb,0x3fd5bec8,0xbfd5bec8,0xbf8ebffb,0xbfed3f44,0xbf44bfed,0x3f44bfed,0xbfedbf44,0xbf443fed,0x3fed3f44,0xbfed3f44,0xbf44bfed,
0x3fedbf44,0x3f443fed,0xbf443fed,0x3fed3f44,0x3f44bfed,0xbfedbf44,0x3fedbf44,0x3f443fed,0xbf8e3ec8,0xbfd5bffb,0x3fd5bffb,0xbf8ebec8,
0xbffb3fd5,0xbec8bf8e,0x3ec8bf8e,0xbffbbfd5,0xbfd53ffb,0x3f8e3ec8,0xbf8e3ec8,0xbfd5bffb,0xbec83f8e,0x3ffb3fd5,0xbffb3fd5,0xbec8bf8e,
0xc000c000,0x0,0x0,0xc0004000,0xc000c000,0x0,0x0,0xc0004000,0xc000c000,0x0,0x0,0xc0004000,
0xc000c000,0x0,0x0,0xc0004000,0xbfd5bffb,0xbf8e3ec8,0x3f8e3ec8,0xbfd53ffb,0xbec8bf8e,0xbffb3fd5,0x3ffb3fd5,0xbec83f8e,
0x3f8e3ec8,0xbfd53ffb,0x3fd53ffb,0x3f8ebec8,0x3ffb3fd5,0xbec83f8e,0x3ec83f8e,0x3ffbbfd5,0xbf44bfed,0xbfed3f44,0x3fed3f44,0xbf443fed,
0x3fed3f44,0xbf443fed,0x3f443fed,0x3fedbf44,0x3f443fed,0x3fedbf44,0xbfedbf44,0x3f44bfed,0xbfedbf44,0x3f44bfed,0xbf44bfed,0xbfed3f44,
0x3ec8bfd5,0xbffb3f8e,0x3ffb3f8e,0x3ec83fd5,0x3f8e3ffb,0x3fd53ec8,0xbfd53ec8,0x3f8ebffb,0xbffbbf8e,0xbec8bfd5,0x3ec8bfd5,0xbffb3f8e,
0x3fd5bec8,0xbf8e3ffb,0x3f8e3ffb,0x3fd53ec8,0x3fb5bfb5,0xbfb53fb5,0x3fb53fb5,0x3fb53fb5,0xbfb53fb5,0x3fb5bfb5,0xbfb5bfb5,0xbfb5bfb5,
0x3fb5bfb5,0xbfb53fb5,0x3fb53fb5,0x3fb53fb5,0xbfb53fb5,0x3fb5bfb5,0xbfb5bfb5,0xbfb5bfb5,0x3ffbbf8e,0xbec83fd5,0x3ec83fd5,0x3ffb3f8e,
0xbfd5bec8,0xbf8ebffb,0x3f8ebffb,0xbfd53ec8,0x3ec83fd5,0x3ffb3f8e,0xbffb3f8e,0x3ec8bfd5,0x3f8ebffb,0xbfd53ec8,0x3fd53ec8,0x3f8e3ffb,
0x3fedbf44,0x3f443fed,0xbf443fed,0x3fed3f44,0x3f44bfed,0xbfedbf44,0x3fedbf44,0x3f443fed,0xbfed3f44,0xbf44bfed,0x3f44bfed,0xbfedbf44,
0xbf443fed,0x3fed3f44,0xbfed3f44,0xbf44bfed,0x3f8ebec8,0x3fd53ffb,0xbfd53ffb,0x3f8e3ec8,0x3ffbbfd5,0x3ec83f8e,0xbec83f8e,0x3ffb3fd5,
0x3fd5bffb,0xbf8ebec8,0x3f8ebec8,0x3fd53ffb,0x3ec8bf8e,0xbffbbfd5,0x3ffbbfd5,0x3ec83f8e,0x40004000,0x3fb5bfb5,0x0,0x3fb5bfb5,
0x40004000,0x3fb5bfb5,0x0,0x3fb5bfb5,0x40004000,0x3fb5bfb5,0x0,0x3fb5bfb5,0x40004000,0x3fb5bfb5,0x0,0x3fb5bfb5,
0x3fc63ff5,0x3fffbfe2,0xbfa2bf15,0x3e49bf71,0x3e493f71,0x3fc6bff5,0xbfffbfe2,0xbfa23f15,0xbfa2bf15,0x3e49bf71,0xbfc6bff5,0xbfff3fe2,
0xbfffbfe2,0xbfa23f15,0xbe49bf71,0xbfc63ff5,0x3ec83fd5,0x3fd5bffb,0xbffbbf8e,0xbf8ebec8,0xbffbbf8e,0xbf8ebec8,0xbec8bfd5,0xbfd53ffb,
0xbec8bfd5,0xbfd53ffb,0x3ffb3f8e,0x3f8e3ec8,0x3ffb3f8e,0x3f8e3ec8,0x3ec83fd5,0x3fd5bffb,0xbf713fa2,0x3f15bfff,0xbfe2bfc6,0xbff53e49,
0xbf15bfff,0xbfe23fc6,0x3ff53e49,0x3f713fa2,0x3fe23fc6,0x3ff5be49,0xbf713fa2,0x3f15bfff,0xbff5be49,0xbf71bfa2,0xbf15bfff,0xbfe23fc6,
0xbfed3f44,0xbf44bfed,0xbf44bfed,0xbfed3f44,0x3fedbf44,0x3f443fed,0x3f443fed,0x3fedbf44,0xbfed3f44,0xbf44bfed,0xbf44bfed,0xbfed3f44,
0x3fedbf44,0x3f443fed,0x3f443fed,0x3fedbf44,0xbff53e49,0xbfe2bfc6,0x3f15bfff,0xbf713fa2,0x3f713fa2,0x3ff53e49,0xbfe23fc6,0xbf15bfff,
0x3f15bfff,0xbf713fa2,0x3ff5be49,0x3fe23fc6,0xbfe23fc6,0xbf15bfff,0xbf71bfa2,0xbff5be49,0xbf8ebec8,0xbffbbf8e,0x3fd5bffb,0x3ec83fd5,
0xbfd53ffb,0xbec8bfd5,0xbf8ebec8,0xbffbbf8e,0x3f8e3ec8,0x3ffb3f8e,0xbfd53ffb,0xbec8bfd5,0x3fd5bffb,0x3ec83fd5,0x3f8e3ec8,0x3ffb3f8e,
0x3e49bf71,0xbfa2bf15,0x3fffbfe2,0x3fc63ff5,0xbfa23f15,0xbfffbfe2,0x3fc6bff5,0x3e493f71,0xbfff3fe2,0xbfc6bff5,0x3e49bf71,0xbfa2bf15,
0xbfc63ff5,0xbe49bf71,0xbfa23f15,0xbfffbfe2,0x0,0xbfb53fb5,0x40004000,0x3fb5bfb5,0x0,0xbfb53fb5,0x40004000,0x3fb5bfb5,
0x0,0xbfb53fb5,0x40004000,0x3fb5bfb5,0x0,0xbfb53fb5,0x40004000,0x3fb5bfb5,0x3fa23f15,0xbe493f71,0x3fc63ff5,0x3fffbfe2,
0x3fff3fe2,0x3fa2bf15,0x3e493f71,0x3fc6bff5,0x3fc63ff5,0x3fffbfe2,0xbfa2bf15,0x3e49bf71,0x3e493f71,0x3fc6bff5,0xbfffbfe2,0xbfa23f15,
0x3ffb3f8e,0x3f8e3ec8,0x3ec83fd5,0x3fd5bffb,0x3ec83fd5,0x3fd5bffb,0xbffbbf8e,0xbf8ebec8,0xbffbbf8e,0xbf8ebec8,0xbec8bfd5,0xbfd53ffb,
0xbec8bfd5,0xbfd53ffb,0x3ffb3f8e,0x3f8e3ec8,0x3fe23fc6,0x3ff5be49,0xbf713fa2,0x3f15bfff,0xbff5be49,0xbf71bfa2,0xbf15bfff,0xbfe23fc6,
0x3f71bfa2,0xbf153fff,0x3fe23fc6,0x3ff5be49,0x3f153fff,0x3fe2bfc6,0xbff5be49,0xbf71bfa2,0x3f443fed,0x3fedbf44,0xbfed3f44,0xbf44bfed,
0xbf44bfed,0xbfed3f44,0x3fedbf44,0x3f443fed,0x3f443fed,0x3fedbf44,0xbfed3f44,0xbf44bfed,0xbf44bfed,0xbfed3f44,0x3fedbf44,0x3f443fed,
0xbf153fff,0x3f71bfa2,0xbff53e49,0xbfe2bfc6,0x3fe2bfc6,0x3f153fff,0x3f713fa2,0x3ff53e49,0xbff53e49,0xbfe2bfc6,0x3f15bfff,0xbf713fa2,
0x3f713fa2,0x3ff53e49,0xbfe23fc6,0xbf15bfff,0xbfd53ffb,0xbec8bfd5,0xbf8ebec8,0xbffbbf8e,0x3f8e3ec8,0x3ffb3f8e,0xbfd53ffb,0xbec8bfd5,
0x3fd5bffb,0x3ec83fd5,0x3f8e3ec8,0x3ffb3f8e,0xbf8ebec8,0xbffbbf8e,0x3fd5bffb,0x3ec83fd5,0xbfff3fe2,0xbfc6bff5,0x3e49bf71,0xbfa2bf15,
0xbfc63ff5,0xbe49bf71,0xbfa23f15,0xbfffbfe2,0xbe493f71,0x3fa23f15,0xbfff3fe2,0xbfc6bff5,0x3fa2bf15,0x3fff3fe2,0xbfc63ff5,0xbe49bf71,
0xc000c000,0xbfb53fb5,0x0,0xbfb53fb5,0xc000c000,0xbfb53fb5,0x0,0xbfb53fb5,0xc000c000,0xbfb53fb5,0x0,0xbfb53fb5,
0xc000c000,0xbfb53fb5,0x0,0xbfb53fb5,0xbfc6bff5,0xbfff3fe2,0x3fa23f15,0xbe493f71,0xbe49bf71,0xbfc63ff5,0x3fff3fe2,0x3fa2bf15,
0x3fa23f15,0xbe493f71,0x3fc63ff5,0x3fffbfe2,0x3fff3fe2,0x3fa2bf15,0x3e493f71,0x3fc6bff5,0xbec8bfd5,0xbfd53ffb,0x3ffb3f8e,0x3f8e3ec8,
0x3ffb3f8e,0x3f8e3ec8,0x3ec83fd5,0x3fd5bffb,0x3ec83fd5,0x3fd5bffb,0xbffbbf8e,0xbf8ebec8,0xbffbbf8e,0xbf8ebec8,0xbec8bfd5,0xbfd53ffb,
0x3f71bfa2,0xbf153fff,0x3fe23fc6,0x3ff5be49,0x3f153fff,0x3fe2bfc6,0xbff5be49,0xbf71bfa2,0xbfe2bfc6,0xbff53e49,0x3f71bfa2,0xbf153fff,
0x3ff53e49,0x3f713fa2,0x3f153fff,0x3fe2bfc6,0x3fedbf44,0x3f443fed,0x3f443fed,0x3fedbf44,0xbfed3f44,0xbf44bfed,0xbf44bfed,0xbfed3f44,
0x3fedbf44,0x3f443fed,0x3f443fed,0x3fedbf44,0xbfed3f44,0xbf44bfed,0xbf44bfed,0xbfed3f44,0x3ff5be49,0x3fe23fc6,0xbf153fff,0x3f71bfa2,
0xbf71bfa2,0xbff5be49,0x3fe2bfc6,0x3f153fff,0xbf153fff,0x3f71bfa2,0xbff53e49,0xbfe2bfc6,0x3fe2bfc6,0x3f153fff,0x3f713fa2,0x3ff53e49,
0x3f8e3ec8,0x3ffb3f8e,0xbfd53ffb,0xbec8bfd5,0x3fd5bffb,0x3ec83fd5,0x3f8e3ec8,0x3ffb3f8e,0xbf8ebec8,0xbffbbf8e,0x3fd5bffb,0x3ec83fd5,
0xbfd53ffb,0xbec8bfd5,0xbf8ebec8,0xbffbbf8e,0xbe493f71,0x3fa23f15,0xbfff3fe2,0xbfc6bff5,0x3fa2bf15,0x3fff3fe2,0xbfc63ff5,0xbe49bf71,
0x3fffbfe2,0x3fc63ff5,0xbe493f71,0x3fa23f15,0x3fc6bff5,0x3e493f71,0x3fa2bf15,0x3fff3fe2,0x0,0x3fb5bfb5,0xc000c000,0xbfb53fb5,
0x0,0x3fb5bfb5,0xc000c000,0xbfb53fb5,0x0,0x3fb5bfb5,0xc000c000,0xbfb53fb5,0x0,0x3fb5bfb5,0xc000c000,0xbfb53fb5,
0xbfa2bf15,0x3e49bf71,0xbfc6bff5,0xbfff3fe2,0xbfffbfe2,0xbfa23f15,0xbe49bf71,0xbfc63ff5,0xbfc6bff5,0xbfff3fe2,0x3fa23f15,0xbe493f71,
0xbe49bf71,0xbfc63ff5,0x3fff3fe2,0x3fa2bf15,0xbffbbf8e,0xbf8ebec8,0xbec8bfd5,0xbfd53ffb,0xbec8bfd5,0xbfd53ffb,0x3ffb3f8e,0x3f8e3ec8,
0x3ffb3f8e,0x3f8e3ec8,0x3ec83fd5,0x3fd5bffb,0x3ec83fd5,0x3fd5bffb,0xbffbbf8e,0xbf8ebec8,0xbfe2bfc6,0xbff53e49,0x3f71bfa2,0xbf153fff,
0x3ff53e49,0x3f713fa2,0x3f153fff,0x3fe2bfc6,0xbf713fa2,0x3f15bfff,0xbfe2bfc6,0xbff53e49,0xbf15bfff,0xbfe23fc6,0x3ff53e49,0x3f713fa2,
0xbf44bfed,0xbfed3f44,0x3fedbf44,0x3f443fed,0x3f443fed,0x3fedbf44,0xbfed3f44,0xbf44bfed,0xbf44bfed,0xbfed3f44,0x3fedbf44,0x3f443fed,
0x3f443fed,0x3fedbf44,0xbfed3f44,0xbf44bfed,0x3f15bfff,0xbf713fa2,0x3ff5be49,0x3fe23fc6,0xbfe23fc6,0xbf15bfff,0xbf71bfa2,0xbff5be49,
0x3ff5be49,0x3fe23fc6,0xbf153fff,0x3f71bfa2,0xbf71bfa2,0xbff5be49,0x3fe2bfc6,0x3f153fff,0x3fd5bffb,0x3ec83fd5,0x3f8e3ec8,0x3ffb3f8e,
0xbf8ebec8,0xbffbbf8e,0x3fd5bffb,0x3ec83fd5,0xbfd53ffb,0xbec8bfd5,0xbf8ebec8,0xbffbbf8e,0x3f8e3ec8,0x3ffb3f8e,0xbfd53ffb,0xbec8bfd5,
0x3fffbfe2,0x3fc63ff5,0xbe493f71,0x3fa23f15,0x3fc6bff5,0x3e493f71,0x3fa2bf15,0x3fff3fe2,0x3e49bf71,0xbfa2bf15,0x3fffbfe2,0x3fc63ff5,
0xbfa23f15,0xbfffbfe2,0x3fc6bff5,0x3e493f71,0x80003f80,0x3f800000,0x80003f80,0x3f800000,0x80003f80,0x3f800000,0x80003f80,0x3f800000,
0x80003f80,0x3f800000,0x80003f80,0x3f800000,0x80003f80,0x3f800000,0x80003f80,0x3f800000,0x80003f80,0x3f800000,0x8000bf80,0xbf800000,
0x3f353f35,0x3f35bf35,0xbf35bf35,0xbf353f35,0x3f800000,0xbf80,0xbf800000,0x3f80,0x3f35bf35,0xbf35bf35,0xbf353f35,0x3f353f35,
0x80003f80,0x3f800000,0x80003f80,0x3f800000,0x3f800000,0xbf80,0x3f800000,0xbf80,0x8000bf80,0xbf800000,0x8000bf80,0xbf800000,
0xbf800000,0x3f80,0xbf800000,0x3f80,0x80003f80,0x3f800000,0x8000bf80,0xbf800000,0x3f35bf35,0xbf35bf35,0xbf353f35,0x3f353f35,
0xbf800000,0x3f80,0x3f800000,0xbf80,0x3f353f35,0x3f35bf35,0xbf35bf35,0xbf353f35,0x80003f80,0x3f800000,0x80003f80,0x3f800000,
0x8000bf80,0xbf800000,0x8000bf80,0xbf800000,0x80003f80,0x3f800000,0x80003f80,0x3f800000,0x8000bf80,0xbf800000,0x8000bf80,0xbf800000,
0x80003f80,0x3f800000,0x8000bf80,0xbf800000,0xbf35bf35,0xbf353f35,0x3f353f35,0x3f35bf35,0x3f800000,0xbf80,0xbf800000,0x3f80,
0xbf353f35,0x3f353f35,0x3f35bf35,0xbf35bf35,0x80003f80,0x3f800000,0x80003f80,0x3f800000,0xbf800000,0x3f80,0xbf800000,0x3f80,
0x8000bf80,0xbf800000,0x8000bf80,0xbf800000,0x3f800000,0xbf80,0x3f800000,0xbf80,0x80003f80,0x3f800000,0x8000bf80,0xbf800000,
0xbf353f35,0x3f353f35,0x3f35bf35,0xbf35bf35,0xbf800000,0x3f80,0x3f800000,0xbf80,0xbf35bf35,0xbf353f35,0x3f353f35,0x3f35bf35,
0x3f803f80,0x80008000,0x80008000,0xbf80bf80,0x3f803f80,0x80008000,0x80008000,0xbf80bf80,0x3f803f80,0x80008000,0x80008000,0xbf80bf80,
0x3f803f80,0x80008000,0x80008000,0xbf80bf80,0x3f353f80,0x3f358000,0x3f358000,0xbf35bf80,0xbf350000,0x3f353f80,0x3f353f80,0x3f358000,
0xbf35bf80,0xbf358000,0xbf358000,0x3f353f80,0x3f350000,0xbf35bf80,0xbf35bf80,0xbf358000,0x3f80,0x3f808000,0x3f808000,0x8000bf80,
0xbf80,0xbf808000,0xbf808000,0x80003f80,0x3f80,0x3f808000,0x3f808000,0x8000bf80,0xbf80,0xbf808000,0xbf808000,0x80003f80,
0xbf353f80,0x3f358000,0x3f358000,0x3f35bf80,0x3f350000,0x3f35bf80,0x3f35bf80,0xbf358000,0x3f35bf80,0xbf358000,0xbf358000,0xbf353f80,
0xbf350000,0xbf353f80,0xbf353f80,0x3f358000,0xbf803f80,0x80008000,0x80008000,0x3f80bf80,0xbf803f80,0x80008000,0x80008000,0x3f80bf80,
0xbf803f80,0x80008000,0x80008000,0x3f80bf80,0xbf803f80,0x80008000,0x80008000,0x3f80bf80,0xbf353f80,0xbf358000,0xbf358000,0x3f35bf80,
0x3f350000,0xbf353f80,0xbf353f80,0xbf358000,0x3f35bf80,0x3f358000,0x3f358000,0xbf353f80,0xbf350000,0x3f35bf80,0x3f35bf80,0x3f358000,
0x3f80,0xbf808000,0xbf808000,0x8000bf80,0xbf80,0x3f808000,0x3f808000,0x80003f80,0x3f80,0xbf808000,0xbf808000,0x8000bf80,
0xbf80,0x3f808000,0x3f808000,0x80003f80,0x3f353f80,0xbf358000,0xbf358000,0xbf35bf80,0xbf350000,0xbf35bf80,0xbf35bf80,0x3f358000,
0xbf35bf80,0x3f358000,0x3f358000,0x3f353f80,0x3f350000,0x3f353f80,0x3f353f80,0xbf358000,0x3f800000,0x0,0x3f800000,0x0,
0x3f800000,0x0,0x3f800000,0x0,0x3f800000,0x0,0x3f800000,0x0,0x3f800000,0x0,0x3f800000,0x0,
0x3f800000,0x0,0x3f7fb10f,0xbd48fb30,0x3f7ec46d,0xbdc8bd36,0x3f7d3aac,0xbe164083,0x3f7b14be,0xbe47c5c2,0x3f7853f8,0xbe78cfcc,
0x3f74fa0b,0xbe94a031,0x3f710908,0xbeac7cd4,0x3f800000,0x0,0x3f7ec46d,0xbdc8bd36,0x3f7b14be,0xbe47c5c2,0x3f74fa0b,0xbe94a031,
0x3f6c835e,0xbec3ef15,0x3f61c598,0xbef15aea,0x3f54db31,0xbf0e39da,0x3f45e403,0xbf226799,0x3f800000,0x0,0x3f7d3aac,0xbe164083,
0x3f74fa0b,0xbe94a031,0x3f676bd8,0xbedae880,0x3f54db31,0xbf0e39da,0x3f3daef9,0xbf2beb4a,0x3f226799,0xbf45e403,0x3f039c3d,0xbf5b941a,
0x3f800000,0x0,0x3f7b14be,0xbe47c5c2,0x3f6c835e,0xbec3ef15,0x3f54db31,0xbf0e39da,0x3f3504f3,0xbf3504f3,0x3f0e39da,0xbf54db31,
0x3ec3ef15,0xbf6c835e,0x3e47c5c2,0xbf7b14be,0x3f800000,0x0,0x3f7853f8,0xbe78cfcc,0x3f61c598,0xbef15aea,0x3f3daef9,0xbf2beb4a,
0x3f0e39da,0xbf54db31,0x3eac7cd4,0xbf710908,0x3dc8bd36,0xbf7ec46d,0xbe164083,0xbf7d3aac,0x3f800000,0x0,0x3f74fa0b,0xbe94a031,
0x3f54db31,0xbf0e39da,0x3f226799,0xbf45e403,0x3ec3ef15,0xbf6c835e,0x3dc8bd36,0xbf7ec46d,0xbe47c5c2,0xbf7b14be,0xbef15aea,0xbf61c598,
0x3f800000,0x0,0x3f710908,0xbeac7cd4,0x3f45e403,0xbf226799,0x3f039c3d,0xbf5b941a,0x3e47c5c2,0xbf7b14be,0xbe164083,0xbf7d3aac,
0xbef15aea,0xbf61c598,0xbf3daef9,0xbf2beb4a,0x3f800000,0x0,0x3f800000,0x0,0x3f800000,0x0,0x3f800000,0x0,
0x3f800000,0x0,0x3f800000,0x0,0x3f800000,0x0,0x3f800000,0x0,0x3f6c835e,0xbec3ef15,0x3f676bd8,0xbedae880,
0x3f61c598,0xbef15aea,0x3f5b941a,0xbf039c3d,0x3f54db31,0xbf0e39da,0x3f4d9f02,0xbf187fc0,0x3f45e403,0xbf226799,0x3f3daef9,0xbf2beb4a,
0x3f3504f3,0xbf3504f3,0x3f226799,0xbf45e403,0x3f0e39da,0xbf54db31,0x3ef15aea,0xbf61c598,0x3ec3ef15,0xbf6c835e,0x3e94a031,0xbf74fa0b,
0x3e47c5c2,0xbf7b14be,0x3dc8bd36,0xbf7ec46d,0x3ec3ef15,0xbf6c835e,0x3e78cfcc,0xbf7853f8,0x3dc8bd36,0xbf7ec46d,0xbd48fb30,0xbf7fb10f,
0xbe47c5c2,0xbf7b14be,0xbeac7cd4,0xbf710908,0xbef15aea,0xbf61c598,0xbf187fc0,0xbf4d9f02,0x0,0xbf800000,0xbe47c5c2,0xbf7b14be,
0xbec3ef15,0xbf6c835e,0xbf0e39da,0xbf54db31,0xbf3504f3,0xbf3504f3,0xbf54db31,0xbf0e39da,0xbf6c835e,0xbec3ef15,0xbf7b14be,0xbe47c5c2,
0xbec3ef15,0xbf6c835e,0xbf187fc0,0xbf4d9f02,0xbf45e403,0xbf226799,0xbf676bd8,0xbedae880,0xbf7b14be,0xbe47c5c2,0xbf7fb10f,0x3d48fb30,
0xbf74fa0b,0x3e94a031,0xbf5b941a,0x3f039c3d,0xbf3504f3,0xbf3504f3,0xbf61c598,0xbef15aea,0xbf7b14be,0xbe47c5c2,0xbf7ec46d,0x3dc8bd36,
0xbf6c835e,0x3ec3ef15,0xbf45e403,0x3f226799,0xbf0e39da,0x3f54db31,0xbe94a031,0x3f74fa0b,0xbf6c835e,0xbec3ef15,0xbf7fb10f,0xbd48fb30,
0xbf74fa0b,0x3e94a031,0xbf4d9f02,0x3f187fc0,0xbf0e39da,0x3f54db31,0xbe78cfcc,0x3f7853f8,0x3dc8bd36,0x3f7ec46d,0x3edae880,0x3f676bd8,
0x80003f80,0x3f800000,0x3f800000,0xbf80,0x3ec43f6d,0x3f6dbec4,0x3f6dbec4,0xbec4bf6d,0x3f353f35,0x3f35bf35,0x3f35bf35,0xbf35bf35,
0x3f6d3ec4,0x3ec4bf6d,0x3ec4bf6d,0xbf6dbec4,0x80003f80,0x3f800000,0xbf800000,0x3f80,0x3f6d3ec4,0x3ec4bf6d,0xbec43f6d,0x3f6d3ec4,
0x3f35bf35,0xbf35bf35,0x3f353f35,0x3f35bf35,0xbec4bf6d,0xbf6d3ec4,0x3f6dbec4,0xbec4bf6d,0x80003f80,0x3f800000,0x3f800000,0xbf80,
0x3f6dbec4,0xbec4bf6d,0xbec4bf6d,0xbf6d3ec4,0xbf35bf35,0xbf353f35,0xbf353f35,0x3f353f35,0xbec43f6d,0x3f6d3ec4,0x3f6d3ec4,0x3ec4bf6d,
0x80003f80,0x3f800000,0xbf800000,0x3f80,0x3ec4bf6d,0xbf6dbec4,0x3f6d3ec4,0x3ec4bf6d,0xbf353f35,0x3f353f35,0xbf35bf35,0xbf353f35,
0x3f6dbec4,0xbec4bf6d,0x3ec43f6d,0x3f6dbec4,0x80003f80,0x3f800000,0x3f800000,0xbf80,0xbec4bf6d,0xbf6d3ec4,0xbf6d3ec4,0x3ec43f6d,
0x3f353f35,0x3f35bf35,0x3f35bf35,0xbf35bf35,0xbf6dbec4,0xbec43f6d,0xbec43f6d,0x3f6d3ec4,0x80003f80,0x3f800000,0xbf800000,0x3f80,
0xbf6dbec4,0xbec43f6d,0x3ec4bf6d,0xbf6dbec4,0x3f35bf35,0xbf35bf35,0x3f353f35,0x3f35bf35,0x3ec43f6d,0x3f6dbec4,0xbf6d3ec4,0x3ec43f6d,
0x80003f80,0x3f800000,0x3f800000,0xbf80,0xbf6d3ec4,0x3ec43f6d,0x3ec43f6d,0x3f6dbec4,0xbf35bf35,0xbf353f35,0xbf353f35,0x3f353f35,
0x3ec4bf6d,0xbf6dbec4,0xbf6dbec4,0xbec43f6d,0x80003f80,0x3f800000,0xbf800000,0x3f80,0xbec43f6d,0x3f6d3ec4,0xbf6dbec4,0xbec43f6d,
0xbf353f35,0x3f353f35,0xbf35bf35,0xbf353f35,0xbf6d3ec4,0x3ec43f6d,0xbec4bf6d,0xbf6d3ec4,0x3f803f80,0x80008000,0x80008000,0xbf80bf80,
0x3f803f80,0x80008000,0x80008000,0xbf80bf80,0x3f803f80,0x80008000,0x80008000,0xbf80bf80,0x3f803f80,0x80008000,0x80008000,0xbf80bf80,
0x3ec43f6d,0x3f6d3ec4,0x3f6d3ec4,0xbec4bf6d,0xbf6dbec4,0x3ec43f6d,0x3ec43f6d,0x3f6d3ec4,0xbec4bf6d,0xbf6dbec4,0xbf6dbec4,0x3ec43f6d,
0x3f6d3ec4,0xbec4bf6d,0xbec4bf6d,0xbf6dbec4,0xbf353f35,0x3f353f35,0x3f353f35,0x3f35bf35,0x3f35bf35,0xbf35bf35,0xbf35bf35,0xbf353f35,
0xbf353f35,0x3f353f35,0x3f353f35,0x3f35bf35,0x3f35bf35,0xbf35bf35,0xbf35bf35,0xbf353f35,0xbf6d3ec4,0xbec43f6d,0xbec43f6d,0x3f6dbec4,
0xbec43f6d,0x3f6dbec4,0x3f6dbec4,0x3ec4bf6d,0x3f6dbec4,0x3ec4bf6d,0x3ec4bf6d,0xbf6d3ec4,0x3ec4bf6d,0xbf6d3ec4,0xbf6d3ec4,0xbec43f6d,
0x0,0xbf803f80,0xbf803f80,0x80008000,0x0,0xbf803f80,0xbf803f80,0x80008000,0x0,0xbf803f80,0xbf803f80,0x80008000,
0x0,0xbf803f80,0xbf803f80,0x80008000,0x3f6dbec4,0xbec43f6d,0xbec43f6d,0xbf6d3ec4,0x3ec4bf6d,0x3f6dbec4,0x3f6dbec4,0xbec43f6d,
0xbf6d3ec4,0x3ec4bf6d,0x3ec4bf6d,0x3f6dbec4,0xbec43f6d,0xbf6d3ec4,0xbf6d3ec4,0x3ec4bf6d,0x3f35bf35,0x3f353f35,0x3f353f35,0xbf353f35,
0xbf353f35,0xbf35bf35,0xbf35bf35,0x3f35bf35,0x3f35bf35,0x3f353f35,0x3f353f35,0xbf353f35,0xbf353f35,0xbf35bf35,0xbf35bf35,0x3f35bf35,
0xbec4bf6d,0x3f6d3ec4,0x3f6d3ec4,0x3ec43f6d,0x3f6d3ec4,0x3ec43f6d,0x3ec43f6d,0xbf6dbec4,0x3ec43f6d,0xbf6dbec4,0xbf6dbec4,0xbec4bf6d,
0xbf6dbec4,0xbec4bf6d,0xbec4bf6d,0x3f6d3ec4,0x3f800000,0x0,0x3f7fec43,0xbcc90ab0,0x3f7fb10f,0xbd48fb30,0x3f7f4e6d,0xbd96a905,
0x3f7ec46d,0xbdc8bd36,0x3f7e1324,0xbdfab273,0x3f7d3aac,0xbe164083,0x3f7c3b28,0xbe2f10a2,0x3f800000,0x0,0x3f7f4e6d,0xbd96a905,
0x3f7d3aac,0xbe164083,0x3f79c79d,0xbe605c13,0x3f74fa0b,0xbe94a031,0x3f6ed89e,0xbeb8442a,0x3f676bd8,0xbedae880,0x3f5ebe05,0xbefc5d27,
0x3f800000,0x0,0x3f7e1324,0xbdfab273,0x3f7853f8,0xbe78cfcc,0x3f6ed89e,0xbeb8442a,0x3f61c598,0xbef15aea,0x3f514d3d,0xbf13682a,
0x3f3daef9,0xbf2beb4a,0x3f273656,0xbf41d870,0x3f800000,0x0,0x3f7c3b28,0xbe2f10a2,0x3f710908,0xbeac7cd4,0x3f5ebe05,0xbefc5d27,
0x3f45e403,0xbf226799,0x3f273656,0xbf41d870,0x3f039c3d,0xbf5b941a,0x3eb8442a,0xbf6ed89e,0x3f800000,0x0,0x3f79c79d,0xbe605c13,
0x3f676bd8,0xbedae880,0x3f49d112,0xbf1d7fd1,0x3f226799,0xbf45e403,0x3ee63375,0xbf64aa59,0x3e78cfcc,0xbf7853f8,0x3cc90ab0,0xbf7fec43,
0x3f800000,0x0,0x3f76ba07,0xbe888e93,0x3f5b941a,0xbf039c3d,0x3f3085bb,0xbf396842,0x3ef15aea,0xbf61c598,0x3e605c13,0xbf79c79d,
0xbd48fb30,0xbf7fb10f,0xbea09ae5,0xbf731447,0x3f800000,0x0,0x3f731447,0xbea09ae5,0x3f4d9f02,0xbf187fc0,0x3f13682a,0xbf514d3d,
0x3e94a031,0xbf74fa0b,0xbcc90ab0,0xbf7fec43,0xbeac7cd4,0xbf710908,0xbf1d7fd1,0xbf49d112,0x3f800000,0x0,0x3f6ed89e,0xbeb8442a,
0x3f3daef9,0xbf2beb4a,0x3ee63375,0xbf64aa59,0x3dc8bd36,0xbf7ec46d,0xbe888e93,0xbf76ba07,0xbf187fc0,0xbf4d9f02,0xbf584853,0xbf08f59b,
0x3f7b14be,0xbe47c5c2,0x3f79c79d,0xbe605c13,0x3f7853f8,0xbe78cfcc,0x3f76ba07,0xbe888e93,0x3f74fa0b,0xbe94a031,0x3f731447,0xbea09ae5,
0x3f710908,0xbeac7cd4,0x3f6ed89e,0xbeb8442a,0x3f54db31,0xbf0e39da,0x3f49d112,0xbf1d7fd1,0x3f3daef9,0xbf2beb4a,0x3f3085bb,0xbf396842,
0x3f226799,0xbf45e403,0x3f13682a,0xbf514d3d,0x3f039c3d,0xbf5b941a,0x3ee63375,0xbf64aa59,0x3f0e39da,0xbf54db31,0x3ee63375,0xbf64aa59,
0x3eac7cd4,0xbf710908,0x3e605c13,0xbf79c79d,0x3dc8bd36,0xbf7ec46d,0xbcc90ab0,0xbf7fec43,0xbe164083,0xbf7d3aac,0xbe888e93,0xbf76ba07,
0x3e47c5c2,0xbf7b14be,0x3cc90ab0,0xbf7fec43,0xbe164083,0xbf7d3aac,0xbea09ae5,0xbf731447,0xbef15aea,0xbf61c598,0xbf1d7fd1,0xbf49d112,
0xbf3daef9,0xbf2beb4a,0xbf584853,0xbf08f59b,0xbe47c5c2,0xbf7b14be,0xbecf7bca,0xbf6a09a7,0xbf187fc0,0xbf4d9f02,0xbf41d870,0xbf273656,
0xbf61c598,0xbef15aea,0xbf76ba07,0xbe888e93,0xbf7fb10f,0xbd48fb30,0xbf7c3b28,0x3e2f10a2,0xbf0e39da,0xbf54db31,0xbf41d870,0xbf273656,
0xbf676bd8,0xbedae880,0xbf7c3b28,0xbe2f10a2,0xbf7ec46d,0x3dc8bd36,0xbf6ed89e,0x3eb8442a,0xbf4d9f02,0x3f187fc0,0xbf1d7fd1,0x3f49d112,
0xbf54db31,0xbf0e39da,0xbf76ba07,0xbe888e93,0xbf7fb10f,0x3d48fb30,0xbf6ed89e,0x3eb8442a,0xbf45e403,0x3f226799,0xbf08f59b,0x3f584853,
0xbe78cfcc,0x3f7853f8,0x3d96a905,0x3f7f4e6d,0xbf7b14be,0xbe47c5c2,0xbf7c3b28,0x3e2f10a2,0xbf5b941a,0x3f039c3d,0xbf1d7fd1,0x3f49d112,
0xbe94a031,0x3f74fa0b,0x3d96a905,0x3f7f4e6d,0x3edae880,0x3f676bd8,0x3f396842,0x3f3085bb,0x80003f80,0x80003f80,0x80003f80,0x80003f80,
0x80003f80,0x80003f80,0x80003f80,0x80003f80,0x80003f80,0x80003f80,0x80003f80,0x80003f80,0x80003f80,0x80003f80,0x80003f80,0x80003f80,
0x3f800000,0x3f800000,0x3f800000,0x3f800000,0x3f800000,0x3f800000,0x3f800000,0x3f800000,0x3f800000,0x3f800000,0x3f800000,0x3f800000,
0x3f800000,0x3f800000,0x3f800000,0x3f800000,0x80003f80,0x3f353f35,0x80003f80,0x3f353f35,0x3f800000,0x3f35bf35,0x3f800000,0x3f35bf35,
0x8000bf80,0xbf35bf35,0x8000bf80,0xbf35bf35,0xbf800000,0xbf353f35,0xbf800000,0xbf353f35,0x3f800000,0x3f35bf35,0x3f800000,0x3f35bf35,
0xbf80,0xbf35bf35,0xbf80,0xbf35bf35,0xbf800000,0xbf353f35,0xbf800000,0xbf353f35,0x3f80,0x3f353f35,0x3f80,0x3f353f35,
0x80003f80,0x3f800000,0x80003f80,0x3f800000,0x8000bf80,0xbf800000,0x8000bf80,0xbf800000,0x80003f80,0x3f800000,0x80003f80,0x3f800000,
0x8000bf80,0xbf800000,0x8000bf80,0xbf800000,0x3f800000,0xbf80,0x3f800000,0xbf80,0xbf800000,0x3f80,0xbf800000,0x3f80,
0x3f800000,0xbf80,0x3f800000,0xbf80,0xbf800000,0x3f80,0xbf800000,0x3f80,0x80003f80,0x3f35bf35,0x80003f80,0x3f35bf35,
0xbf800000,0x3f353f35,0xbf800000,0x3f353f35,0x8000bf80,0xbf353f35,0x8000bf80,0xbf353f35,0x3f800000,0xbf35bf35,0x3f800000,0xbf35bf35,
0x3f800000,0xbf35bf35,0x3f800000,0xbf35bf35,0x3f80,0x3f35bf35,0x3f80,0x3f35bf35,0xbf800000,0x3f353f35,0xbf800000,0x3f353f35,
0xbf80,0xbf353f35,0xbf80,0xbf353f35,0x80003f80,0x3ec43f6d,0x8000bf80,0xbec4bf6d,0x3f353f35,0x3f6d3ec4,0xbf35bf35,0xbf6dbec4,
0x3f800000,0x3f6dbec4,0xbf800000,0xbf6d3ec4,0x3f35bf35,0x3ec4bf6d,0xbf353f35,0xbec43f6d,0x3f800000,0x3f6dbec4,0xbf800000,0xbf6d3ec4,
0x3f35bf35,0x3ec4bf6d,0xbf353f35,0xbec43f6d,0xbf80,0xbec4bf6d,0x3f80,0x3ec43f6d,0xbf35bf35,0xbf6dbec4,0x3f353f35,0x3f6d3ec4,
0x80003f80,0x3f6d3ec4,0x8000bf80,0xbf6dbec4,0x3f35bf35,0xbec4bf6d,0xbf353f35,0x3ec43f6d,0xbf800000,0xbec43f6d,0x3f800000,0x3ec4bf6d,
0x3f353f35,0x3f6dbec4,0xbf35bf35,0xbf6d3ec4,0x3f800000,0x3ec4bf6d,0xbf800000,0xbec43f6d,0xbf35bf35,0xbf6d3ec4,0x3f353f35,0x3f6dbec4,
0x3f80,0x3f6d3ec4,0xbf80,0xbf6dbec4,0x3f35bf35,0xbec4bf6d,0xbf353f35,0x3ec43f6d,0x80003f80,0x3f6dbec4,0x8000bf80,0xbf6d3ec4,
0xbf35bf35,0xbec43f6d,0x3f353f35,0x3ec4bf6d,0x3f800000,0xbec4bf6d,0xbf800000,0x3ec43f6d,0xbf353f35,0x3f6d3ec4,0x3f35bf35,0xbf6dbec4,
0x3f800000,0xbec4bf6d,0xbf800000,0x3ec43f6d,0xbf353f35,0x3f6d3ec4,0x3f35bf35,0xbf6dbec4,0xbf80,0xbf6d3ec4,0x3f80,0x3f6dbec4,
0x3f353f35,0x3ec4bf6d,0xbf35bf35,0xbec43f6d,0x80003f80,0x3ec4bf6d,0x8000bf80,0xbec43f6d,0xbf353f35,0x3f6dbec4,0x3f35bf35,0xbf6d3ec4,
0xbf800000,0x3f6d3ec4,0x3f800000,0xbf6dbec4,0xbf35bf35,0x3ec43f6d,0x3f353f35,0xbec4bf6d,0x3f800000,0xbf6dbec4,0xbf800000,0x3f6d3ec4,
0x3f353f35,0xbec4bf6d,0xbf35bf35,0x3ec43f6d,0x3f80,0x3ec4bf6d,0xbf80,0xbec43f6d,0xbf353f35,0x3f6dbec4,0x3f35bf35,0xbf6d3ec4,
0x80003f80,0x8000bf80,0x80003f80,0x8000bf80,0x80003f80,0x8000bf80,0x80003f80,0x8000bf80,0x80003f80,0x8000bf80,0x80003f80,0x8000bf80,
0x80003f80,0x8000bf80,0x80003f80,0x8000bf80,0x3f800000,0xbf800000,0x3f800000,0xbf800000,0x3f800000,0xbf800000,0x3f800000,0xbf800000,
0x3f800000,0xbf800000,0x3f800000,0xbf800000,0x3f800000,0xbf800000,0x3f800000,0xbf800000,0x80003f80,0xbf35bf35,0x80003f80,0xbf35bf35,
0x3f800000,0xbf353f35,0x3f800000,0xbf353f35,0x8000bf80,0x3f353f35,0x8000bf80,0x3f353f35,0xbf800000,0x3f35bf35,0xbf800000,0x3f35bf35,
0x3f800000,0xbf353f35,0x3f800000,0xbf353f35,0xbf80,0x3f353f35,0xbf80,0x3f353f35,0xbf800000,0x3f35bf35,0xbf800000,0x3f35bf35,
0x3f80,0xbf35bf35,0x3f80,0xbf35bf35,0x80003f80,0xbf800000,0x80003f80,0xbf800000,0x8000bf80,0x3f800000,0x8000bf80,0x3f800000,
0x80003f80,0xbf800000,0x80003f80,0xbf800000,0x8000bf80,0x3f800000,0x8000bf80,0x3f800000,0x3f800000,0x3f80,0x3f800000,0x3f80,
0xbf800000,0xbf80,0xbf800000,0xbf80,0x3f800000,0x3f80,0x3f800000,0x3f80,0xbf800000,0xbf80,0xbf800000,0xbf80,
0x80003f80,0xbf353f35,0x80003f80,0xbf353f35,0xbf800000,0xbf35bf35,0xbf800000,0xbf35bf35,0x8000bf80,0x3f35bf35,0x8000bf80,0x3f35bf35,
0x3f800000,0x3f353f35,0x3f800000,0x3f353f35,0x3f800000,0x3f353f35,0x3f800000,0x3f353f35,0x3f80,0xbf353f35,0x3f80,0xbf353f35,
0xbf800000,0xbf35bf35,0xbf800000,0xbf35bf35,0xbf80,0x3f35bf35,0xbf80,0x3f35bf35,0x80003f80,0xbec4bf6d,0x8000bf80,0x3ec43f6d,
0x3f353f35,0xbf6dbec4,0xbf35bf35,0x3f6d3ec4,0x3f800000,0xbf6d3ec4,0xbf800000,0x3f6dbec4,0x3f35bf35,0xbec43f6d,0xbf353f35,0x3ec4bf6d,
0x3f800000,0xbf6d3ec4,0xbf800000,0x3f6dbec4,0x3f35bf35,0xbec43f6d,0xbf353f35,0x3ec4bf6d,0xbf80,0x3ec43f6d,0x3f80,0xbec4bf6d,
0xbf35bf35,0x3f6d3ec4,0x3f353f35,0xbf6dbec4,0x80003f80,0xbf6dbec4,0x8000bf80,0x3f6d3ec4,0x3f35bf35,0x3ec43f6d,0xbf353f35,0xbec4bf6d,
0xbf800000,0x3ec4bf6d,0x3f800000,0xbec43f6d,0x3f353f35,0xbf6d3ec4,0xbf35bf35,0x3f6dbec4,0x3f800000,0xbec43f6d,0xbf800000,0x3ec4bf6d,
0xbf35bf35,0x3f6dbec4,0x3f353f35,0xbf6d3ec4,0x3f80,0xbf6dbec4,0xbf80,0x3f6d3ec4,0x3f35bf35,0x3ec43f6d,0xbf353f35,0xbec4bf6d,
0x80003f80,0xbf6d3ec4,0x8000bf80,0x3f6dbec4,0xbf35bf35,0x3ec4bf6d,0x3f353f35,0xbec43f6d,0x3f800000,0x3ec43f6d,0xbf800000,0xbec4bf6d,
0xbf353f35,0xbf6dbec4,0x3f35bf35,0x3f6d3ec4,0x3f800000,0x3ec43f6d,0xbf800000,0xbec4bf6d,0xbf353f35,0xbf6dbec4,0x3f35bf35,0x3f6d3ec4,
0xbf80,0x3f6dbec4,0x3f80,0xbf6d3ec4,0x3f353f35,0xbec43f6d,0xbf35bf35,0x3ec4bf6d,0x80003f80,0xbec43f6d,0x8000bf80,0x3ec4bf6d,
0xbf353f35,0xbf6d3ec4,0x3f35bf35,0x3f6dbec4,0xbf800000,0xbf6dbec4,0x3f800000,0x3f6d3ec4,0xbf35bf35,0xbec4bf6d,0x3f353f35,0x3ec43f6d,
0x3f800000,0x3f6d3ec4,0xbf800000,0xbf6dbec4,0x3f353f35,0x3ec43f6d,0xbf35bf35,0xbec4bf6d,0x3f80,0xbec43f6d,0xbf80,0x3ec4bf6d,
0xbf353f35,0xbf6d3ec4,0x3f35bf35,0x3f6dbec4,0xbf253f44,0x3f253f44,0x3eafbf71,0xbeafbf71,0xbf7c3e32,0x3f7c3e32,0xbf253f44,0x3f253f44,
0xbf5ebf00,0x3f5ebf00,0x3f5ebf00,0xbf5ebf00,0xbeafbf71,0x3eafbf71,0xbf7c3e32,0x3f7c3e32,0x3f443f25,0x3f44bf25,0xbf71beaf,0xbf713eaf,
0x3e323f7c,0x3e32bf7c,0x3f443f25,0x3f44bf25,0xbf003f5e,0xbf00bf5e,0xbf00bf5e,0xbf003f5e,0xbf713eaf,0xbf71beaf,0x3e323f7c,0x3e32bf7c,
0xbf7c3e32,0x3f7c3e32,0x3f5ebf00,0xbf5ebf00,0xbeafbf71,0x3eafbf71,0xbf5ebf00,0x3f5ebf00,0x3f5ebf00,0xbf5ebf00,0x3f80,0x3f80,
0x3f253f44,0xbf253f44,0x3f5ebf00,0xbf5ebf00,0x3e323f7c,0x3e32bf7c,0xbf00bf5e,0xbf003f5e,0xbf713eaf,0xbf71beaf,0xbf003f5e,0xbf00bf5e,
0xbf00bf5e,0xbf003f5e,0x3f808000,0x3f808000,0x3f44bf25,0x3f443f25,0xbf00bf5e,0xbf003f5e,0xbf5ebf00,0x3f5ebf00,0x3f7c3e32,0xbf7c3e32,
0x3f5ebf00,0xbf5ebf00,0x3eafbf71,0xbeafbf71,0x3f80,0x3f80,0xbf5ebf00,0x3f5ebf00,0xbf5ebf00,0x3f5ebf00,0xbf253f44,0x3f253f44,
0xbf003f5e,0xbf00bf5e,0x3e32bf7c,0x3e323f7c,0xbf00bf5e,0xbf003f5e,0xbf71beaf,0xbf713eaf,0x3f808000,0x3f808000,0xbf003f5e,0xbf00bf5e,
0xbf003f5e,0xbf00bf5e,0x3f443f25,0x3f44bf25,0xbeafbf71,0x3eafbf71,0x3f253f44,0xbf253f44,0x3f253f44,0xbf253f44,0x3f7c3e32,0xbf7c3e32,
0xbf5ebf00,0x3f5ebf00,0x3f5ebf00,0xbf5ebf00,0x3f7c3e32,0xbf7c3e32,0x3eafbf71,0xbeafbf71,0xbf713eaf,0xbf71beaf,0x3f44bf25,0x3f443f25,
0x3f44bf25,0x3f443f25,0x3e32bf7c,0x3e323f7c,0xbf003f5e,0xbf00bf5e,0xbf00bf5e,0xbf003f5e,0x3e32bf7c,0x3e323f7c,0xbf71beaf,0xbf713eaf,
0x218,0x708,0x28,0x908,0x410,0x500,0x28,0x908,0x600,0x2f0,0x28,0x908,
0x7e0,0x130,0x28,0x908,0x330,0xd0,0x110,0x110,0x558,0x2e0,0x110,0x110,
0x6f0,0x4d8,0x110,0x110,0x8f8,0x720,0x110,0x110,0x420,0x40,0x260,0x260,
0x640,0x1b8,0x260,0x260,0x838,0x418,0x260,0x260,0x788,0x5c8,0x260,0x260,
0x568,0x168,0x338,0x338,0x750,0xf8,0x338,0x338,0x8a8,0x2a8,0x338,0x338,
0x6c8,0x490,0x338,0x338,0x680,0x288,0x498,0x498,0x890,0x78,0x498,0x498,
0x7a8,0x180,0x498,0x498,0x570,0x3b0,0x498,0x498,0x7a0,0x3b8,0x5c0,0x5c0,
0x860,0x1d0,0x5c0,0x5c0,0x688,0x98,0x5c0,0x5c0,0x4b0,0x240,0x5c0,0x5c0,
0x8e8,0x4c8,0x6b0,0x6b0,0x758,0x290,0x6b0,0x6b0,0x550,0xa0,0x6b0,0x6b0,
0x340,0x160,0x6b0,0x6b0,0x878,0x5f0,0x808,0x808,0x618,0x3e8,0x808,0x808,
0x448,0x228,0x808,0x808,0x238,0x58,0x808,0x808,0x258,0x1c0,0x30,0x30,
0x440,0x398,0x30,0x30,0x698,0x5a0,0x30,0x30,0x850,0x790,0x30,0x30,
0x320,0x88,0x188,0x188,0x590,0x2d8,0x188,0x188,0x748,0x468,0x188,0x188,
0x888,0x678,0x188,0x188,0x4a8,0x80,0x298,0x298,0x668,0x148,0x298,0x298,
0x880,0x370,0x298,0x298,0x778,0x560,0x298,0x298,0x5e0,0x1b0,0x380,0x380,
0x7b8,0x38,0x380,0x380,0x830,0x250,0x380,0x380,0x670,0x428,0x380,0x380,
0x6d0,0x2b0,0x4c0,0x4c0,0x918,0xc8,0x4c0,0x4c0,0x6e8,0x118,0x4c0,0x4c0,
0x528,0x360,0x4c0,0x4c0,0x800,0x3f8,0x5e8,0x5e8,0x7f0,0x1f0,0x5e8,0x5e8,
0x608,0x50,0x5e8,0x5e8,0x3c8,0x220,0x5e8,0x5e8,0x8c0,0x510,0x6f8,0x6f8,
0x730,0x308,0x6f8,0x6f8,0x4f8,0x128,0x6f8,0x6f8,0x310,0xc0,0x6f8,0x6f8,
0x7d8,0x638,0x870,0x870,0x5b8,0x458,0x870,0x870,0x3e0,0x1e8,0x870,0x870,
0x1a0,0x0,0x870,0x870,0x2a0,0x178,0x60,0x60,0x470,0x358,0x60,0x60,
0x658,0x580,0x60,0x60,0x8b8,0x740,0x60,0x60,0x388,0x48,0x1c8,0x1c8,
0x5f8,0x268,0x1c8,0x1c8,0x7b0,0x438,0x1c8,0x1c8,0x828,0x660,0x1c8,0x1c8,
0x4e0,0xf0,0x2d0,0x2d0,0x6c0,0x108,0x2d0,0x2d0,0x8c8,0x328,0x2d0,0x2d0,
0x700,0x518,0x2d0,0x2d0,0x5d0,0x210,0x3d8,0x3d8,0x818,0x20,0x3d8,0x3d8,
0x7e8,0x230,0x3d8,0x3d8,0x610,0x3d0,0x3d8,0x3d8,0x738,0x2e8,0x538,0x538,
0x8f0,0x100,0x538,0x538,0x710,0xb8,0x538,0x538,0x4e8,0x318,0x538,0x538,
0x848,0x430,0x628,0x628,0x7d0,0x1e0,0x628,0x628,0x5a8,0x8,0x628,0x628,
0x408,0x1a8,0x628,0x628,0x8b0,0x540,0x770,0x770,0x6d8,0x378,0x770,0x770,
0x460,0x190,0x770,0x770,0x280,0xd8,0x770,0x770,0x798,0x650,0x820,0x820,
0x578,0x4a0,0x820,0x820,0x3a0,0x248,0x820,0x820,0x140,0x70,0x820,0x820,
0x2c8,0x120,0xe8,0xe8,0x4f0,0x368,0xe8,0xe8,0x6b8,0x548,0xe8,0xe8,
0x8e0,0x6e0,0xe8,0xe8,0x400,0x18,0x200,0x200,0x5d8,0x1f8,0x200,0x200,
0x7f8,0x3c0,0x200,0x200,0x810,0x630,0x200,0x200,0x508,0x138,0x2f8,0x2f8,
0x728,0xa8,0x2f8,0x2f8,0x8d0,0x300,0x2f8,0x2f8,0x718,0x4d0,0x2f8,0x2f8,
0x620,0x208,0x450,0x450,0x868,0x10,0x450,0x450,0x7c0,0x1d8,0x450,0x450,
0x5b0,0x3f0,0x450,0x450,0x760,0x348,0x520,0x520,0x8a0,0x150,0x520,0x520,
0x6a8,0xb0,0x520,0x520,0x488,0x2c0,0x520,0x520,0x840,0x480,0x690,0x690,
0x780,0x270,0x690,0x690,0x598,0x90,0x690,0x690,0x390,0x198,0x690,0x690,
0x858,0x588,0x7c8,0x7c8,0x648,0x3a8,0x7c8,0x7c8,0x4b8,0x158,0x7c8,0x7c8,
0x278,0x68,0x7c8,0x7c8,0x768,0x6a0,0x898,0x898,0x530,0x478,0x898,0x898,
0x350,0x2b8,0x898,0x898,0x170,0xe0,0x898,0x898,0x28,0x18,0x20,0x50,
0x58,0x0,0x8,0x10,0x40,0x30,0x48,0x38,0x38,0x8,0x10,0x30,
0x18,0x20,0x0,0x28,0x58,0x10,0x38,0x40,0x0,0x28,0x50,0x48,
0x30,0x8,0x18,0x20,0x30,0x28,0x0,0x38,0x10,0x20,0x8,0x18,
0x20,0x30,0x50,0x10,0x28,0x48,0x38,0x8,0x40,0x58,0x0,0x18,
0x30,0x10,0x28,0x20,0x18,0x38,0x8,0x0,0x48,0x10,0x30,0x20,
0x38,0x18,0x50,0x40,0x58,0x8,0x0,0x28,0x20,0x18,0x28,0x10,
0x0,0x38,0x8,0x30,0x8,0x18,0x20,0x58,0x28,0x40,0x0,0x38,
0x10,0x30,0x50,0x48,0x0,0x20,0x38,0x30,0x10,0x28,0x8,0x18,
0x10,0x48,0x8,0x40,0x20,0x30,0x58,0x28,0x18,0x0,0x38,0x50,
0x30,0x10,0x20,0x28,0x38,0x0,0x8,0x18,0x58,0x30,0x48,0x20,
0x28,0x38,0x18,0x40,0x50,0x0,0x10,0x8,0x28,0x38,0x10,0x30,
0x0,0x20,0x18,0x8,0x50,0x58,0x40,0x20,0x38,0x48,0x10,0x8,
0x30,0x28,0x0,0x18,0x8,0x0,0x20,0x30,0x18,0x10,0x28,0x38,
0x0,0x10,0x38,0x8,0x58,0x48,0x18,0x28,0x50,0x30,0x40,0x20,
0x8,0x30,0x20,0x0,0x10,0x38,0x18,0x28,0x20,0x40,0x58,0x0,
0x28,0x10,0x8,0x18,0x50,0x48,0x30,0x38,0x0,0x30,0x10,0x8,
0x18,0x38,0x28,0x20,0x0,0x58,0x20,0x30,0x48,0x8,0x10,0x50,
0x40,0x28,0x18,0x38,0x28,0x8,0x38,0x0,0x10,0x30,0x20,0x18,
0x40,0x38,0x30,0x50,0x28,0x18,0x58,0x48,0x10,0x0,0x20,0x8,
0x18,0x28,0x30,0x20,0x10,0x8,0x0,0x38,0x28,0x0,0x18,0x48,
0x20,0x38,0x30,0x10,0x8,0x40,0x50,0x58,0x28,0x20,0x38,0x18,
0x0,0x30,0x8,0x10,0x58,0x50,0x28,0x48,0x18,0x30,0x8,0x10,
0x40,0x38,0x0,0x20,0x10,0x0,0x38,0x8,0x28,0x20,0x30,0x18,
0x28,0x58,0x8,0x20,0x38,0x10,0x30,0x0,0x48,0x18,0x50,0x40,
0x0,0x8,0x10,0x18,0x20,0x28,0x30,0x38,0x0,0x0,0x0,0x0,
0x0,0x0,0x0,0x0,0x0,0x0,0x0,0x0,0x0,0x0,0x0,0x0,
0x0,0x0,0x0,0x0,
};
constexpr int TB_F = 0, TB_E = 512, TB_P2 = 1024, TB_9 = 1408, TB_L3 = 1440, TB_POS = 1568;

enum { C_EP = 0, C_Z1 = 32, C_Z2 = 96, C_H3 = 128, C_U = 160, C_X = 288, C_TOTAL = 512 };
struct Scratch {
  unsigned cnt[C_TOTAL];
  uint32_t moda[8 * 2 * D_];
  uint32_t mod[4 * D_ + 256];
  uint32_t z1[120 * 5120];
  uint32_t z2[128 * 4800];
  uint8_t h3[32 * 18 * 4096];
  uint8_t u[72 * D_ * 128];
};
__device__ __align__(1024) Scratch g_s;

constexpr int HOLDA = 5;
constexpr int X1K = 10;
constexpr int NV1 = 12;
constexpr int NV2 = 20;
constexpr int W0N = 3;
constexpr int TRK0 = 50;
constexpr int TRKC = 350;
constexpr int HD1 = 150;
constexpr int EH = 7;

struct Maps { CUtensorMap z1, z2[2], w1a, w1b, h3, w2, wf[4], wm; };
struct Params {
  const __nv_bfloat16 *x, *c, *wmod;
  Scratch* s;
  const uint4* tab;
  const __nv_bfloat16 *wr, *wi, *w1, *w2, *b1, *b2;
  uint32_t* out;
};

__device__ __forceinline__ uint32_t smem_u32(const void* p) { return (uint32_t)__cvta_generic_to_shared(p); }
__device__ __forceinline__ void mbar_init(uint32_t b, int c) { asm volatile("mbarrier.init.shared::cta.b64 [%0], %1;" ::"r"(b), "r"(c)); }
__device__ __forceinline__ void mbar_expect(uint32_t b, int bytes) { asm volatile("mbarrier.arrive.expect_tx.shared::cta.b64 _, [%0], %1;" ::"r"(b), "r"(bytes) : "memory"); }
__device__ __forceinline__ void mbar_arrive(uint32_t b) { asm volatile("mbarrier.arrive.shared::cta.b64 _, [%0];" ::"r"(b) : "memory"); }
__device__ __forceinline__ void mbar_wait(uint32_t b, int ph) {
  asm volatile("{\n.reg .pred p;\n.reg .u32 it;\nmov.u32 it, 0;\nW:\nmbarrier.try_wait.parity.shared::cta.b64 p, [%0], %1;\n"
               "@p bra.uni D;\nadd.u32 it, it, 1;\nsetp.lt.u32 p, it, 0x400000;\n@p bra.uni W;\ntrap;\nD:\n}" ::"r"(b), "r"(ph) : "memory");
}
__device__ __forceinline__ uint32_t mbar_test(uint32_t b, int ph) {
  uint32_t ok;
  asm volatile("{\n.reg .pred p;\nmbarrier.test_wait.parity.shared::cta.b64 p, [%1], %2;\nselp.u32 %0, 1, 0, p;\n}\n" : "=r"(ok) : "r"(b), "r"(ph) : "memory");
  return ok;
}
__device__ __forceinline__ void tma2d(uint32_t dst, const CUtensorMap* m, int c0, int c1, uint32_t bar) {
  asm volatile("cp.async.bulk.tensor.2d.shared::cluster.global.mbarrier::complete_tx::bytes [%0], [%1, {%3, %4}], [%2];" ::"r"(dst), "l"(m), "r"(bar), "r"(c0), "r"(c1) : "memory");
}
__device__ __forceinline__ uint64_t pol_ef() { uint64_t p; asm("createpolicy.fractional.L2::evict_first.b64 %0, 1.0;" : "=l"(p)); return p; }
__device__ __forceinline__ void tma3d_ef(uint32_t dst, const CUtensorMap* m, int c1, int c2, uint32_t bar) {
  asm volatile("cp.async.bulk.tensor.3d.shared::cluster.global.mbarrier::complete_tx::bytes.L2::cache_hint [%0], [%1, {%3, %4, %5}], [%2], %6;" ::"r"(dst), "l"(m), "r"(bar), "r"(0), "r"(c1), "r"(c2), "l"(pol_ef()) : "memory");
}
__device__ __forceinline__ void tma4d_ef(uint32_t dst, const CUtensorMap* m, int c1, int c2, int c3, uint32_t bar) {
  asm volatile("cp.async.bulk.tensor.4d.shared::cluster.global.mbarrier::complete_tx::bytes.L2::cache_hint [%0], [%1, {%3, %7, %4, %5}], [%2], %6;" ::"r"(dst), "l"(m), "r"(bar), "r"(0), "r"(c2), "r"(c3), "l"(pol_ef()), "r"(c1) : "memory");
}
__device__ __forceinline__ void bulk_ld(uint32_t dst, const void* src, int bytes, uint32_t bar) {
  asm volatile("cp.async.bulk.shared::cluster.global.mbarrier::complete_tx::bytes [%0], [%1], %2, [%3];" ::"r"(dst), "l"(src), "r"(bytes), "r"(bar) : "memory");
}
__device__ __forceinline__ void bulk_st(void* dst, uint32_t src, int bytes) {
  asm volatile("cp.async.bulk.global.shared::cta.bulk_group [%0], [%1], %2;" ::"l"(dst), "r"(src), "r"(bytes) : "memory");
}
__device__ __forceinline__ void tma_st2d(const CUtensorMap* m, uint32_t src, int c0, int c1) {
  asm volatile("cp.async.bulk.tensor.2d.global.shared::cta.bulk_group [%0, {%2, %3}], [%1];" ::"l"(m), "r"(src), "r"(c0), "r"(c1) : "memory");
}
__device__ __forceinline__ void tma_st3d(const CUtensorMap* m, uint32_t src, int c0, int c1, int c2) {
  asm volatile("cp.async.bulk.tensor.3d.global.shared::cta.bulk_group [%0, {%2, %3, %4}], [%1];" ::"l"(m), "r"(src), "r"(c0), "r"(c1), "r"(c2) : "memory");
}
__device__ __forceinline__ void bulk_commit_wait() {
  asm volatile("cp.async.bulk.commit_group;" ::: "memory");
  asm volatile("cp.async.bulk.wait_group 0;" ::: "memory");
}
__device__ __forceinline__ void prefetch_l2(const void* p, int bytes) {
  asm volatile("cp.async.bulk.prefetch.L2.global [%0], %1;" ::"l"(p), "r"(bytes) : "memory");
}
__device__ __forceinline__ void wg_fence() { asm volatile("wgmma.fence.sync.aligned;" ::: "memory"); }
__device__ __forceinline__ void wg_commit() { asm volatile("wgmma.commit_group.sync.aligned;" ::: "memory"); }
template <int N> __device__ __forceinline__ void wg_wait() { asm volatile("wgmma.wait_group.sync.aligned %0;" ::"n"(N) : "memory"); }
template <int N> __device__ __forceinline__ void reg_fence(float (&d)[N]) {
#pragma unroll
  for (int i = 0; i < N; i++) asm volatile("" : "+f"(d[i])::"memory");
}
__device__ __forceinline__ void fence_async_smem() { asm volatile("fence.proxy.async.shared::cta;" ::: "memory"); }
__device__ __forceinline__ void fence_async_glb() { asm volatile("fence.proxy.async.global;" ::: "memory"); }
__device__ __forceinline__ uint32_t ld_rlx(const void* p) { uint32_t v; asm volatile("ld.relaxed.gpu.global.b32 %0, [%1];" : "=r"(v) : "l"(p) : "memory"); return v; }
__device__ __forceinline__ uint2 ld_rlx2(const void* p) { uint2 v; asm volatile("ld.relaxed.gpu.global.v2.b32 {%0,%1}, [%2];" : "=r"(v.x), "=r"(v.y) : "l"(p) : "memory"); return v; }
__device__ __forceinline__ uint4 ld_rlx4(const void* p) { uint4 v; asm volatile("ld.relaxed.gpu.global.v4.b32 {%0,%1,%2,%3}, [%4];" : "=r"(v.x), "=r"(v.y), "=r"(v.z), "=r"(v.w) : "l"(p) : "memory"); return v; }
__device__ __forceinline__ uint32_t ld_nc(const void* p) { uint32_t v; asm volatile("ld.global.nc.L1::no_allocate.b32 %0, [%1];" : "=r"(v) : "l"(p) : "memory"); return v; }
__device__ __forceinline__ uint4 ld_nc4(const void* p) { uint4 v; asm volatile("ld.global.nc.v4.b32 {%0,%1,%2,%3}, [%4];" : "=r"(v.x), "=r"(v.y), "=r"(v.z), "=r"(v.w) : "l"(p) : "memory"); return v; }
__device__ __forceinline__ uint32_t lds(uint32_t a) { uint32_t v; asm volatile("ld.shared.b32 %0, [%1];" : "=r"(v) : "r"(a) : "memory"); return v; }
__device__ __forceinline__ uint2 lds2(uint32_t a) { uint2 v; asm volatile("ld.shared.v2.b32 {%0,%1}, [%2];" : "=r"(v.x), "=r"(v.y) : "r"(a) : "memory"); return v; }
__device__ __forceinline__ void lds2_if(int on, uint2& v, uint32_t a) { asm volatile("{\n.reg .pred p;\nsetp.ne.u32 p, %3, 0;\n@p ld.shared.v2.b32 {%0,%1}, [%2];\n}" : "+r"(v.x), "+r"(v.y) : "r"(a), "r"(on) : "memory"); }
__device__ __forceinline__ uint4 lds4(uint32_t a) { uint4 v; asm volatile("ld.shared.v4.b32 {%0,%1,%2,%3}, [%4];" : "=r"(v.x), "=r"(v.y), "=r"(v.z), "=r"(v.w) : "r"(a) : "memory"); return v; }
__device__ __forceinline__ float lds_bf(uint32_t a) { uint32_t v; asm volatile("ld.shared.u16 %0, [%1];" : "=r"(v) : "r"(a) : "memory"); return __uint_as_float(v << 16); }
__device__ __forceinline__ void sts(uint32_t a, uint32_t v) { asm volatile("st.shared.b32 [%0], %1;" ::"r"(a), "r"(v) : "memory"); }
__device__ __forceinline__ void sts2(uint32_t a, uint32_t v0, uint32_t v1) { asm volatile("st.shared.v2.b32 [%0], {%1,%2};" ::"r"(a), "r"(v0), "r"(v1) : "memory"); }
__device__ __forceinline__ void sts4(uint32_t a, uint32_t v0, uint32_t v1, uint32_t v2, uint32_t v3) { asm volatile("st.shared.v4.b32 [%0], {%1,%2,%3,%4};" ::"r"(a), "r"(v0), "r"(v1), "r"(v2), "r"(v3) : "memory"); }
__device__ __forceinline__ void bar_sync(int id, int n) { asm volatile("bar.sync %0, %1;" ::"r"(id), "r"(n) : "memory"); }
__device__ __forceinline__ void bar_arrive(int id, int n) { asm volatile("bar.arrive %0, %1;" ::"r"(id), "r"(n) : "memory"); }
__device__ __forceinline__ void red_add(unsigned* p, unsigned v) { asm volatile("red.relaxed.gpu.global.add.u32 [%0], %1;" ::"l"(p), "r"(v) : "memory"); }
__device__ __forceinline__ bool any(bool p) { return __any_sync(0xffffffffu, p); }
__device__ __forceinline__ void pause(unsigned clks) {
  asm volatile("{\n.reg .pred p;\n.reg .u32 a, b;\nmov.u32 a, %%clock;\nW:\nmov.u32 b, %%clock;\nsub.u32 b, b, a;\nsetp.lt.s32 p, b, %0;\n@p bra.uni W;\n}" ::"r"(clks) : "memory");
}
__device__ __forceinline__ void red_bf16x8(uint32_t* p, uint32_t a, uint32_t b, uint32_t c, uint32_t d) {
  asm volatile("red.relaxed.gpu.global.add.noftz.v4.bf16x2 [%0], {%1,%2,%3,%4};" ::"l"(p), "r"(a), "r"(b), "r"(c), "r"(d) : "memory");
}
__device__ __forceinline__ void red_bf16x4(uint32_t* p, uint32_t a, uint32_t b) {
  asm volatile("red.relaxed.gpu.global.add.noftz.v2.bf16x2 [%0], {%1,%2};" ::"l"(p), "r"(a), "r"(b) : "memory");
}
constexpr int SPIN_MAX = 1 << 20;
__device__ __forceinline__ uint32_t ld_acq(const void* p) { uint32_t v; asm volatile("ld.acquire.gpu.global.b32 %0, [%1];" : "=r"(v) : "l"(p) : "memory"); return v; }
template <bool ACQ = false> __device__ __forceinline__ void wait_cnt(const unsigned* p, unsigned target) {
  int it = 0;
  while (any((int)((ACQ ? ld_acq(p) : ld_rlx(p)) - target) < 0) && ++it < SPIN_MAX) {}
}
__device__ __forceinline__ uint32_t pack_bf16(float lo, float hi) { uint32_t r; asm("cvt.rn.bf16x2.f32 %0, %1, %2;" : "=r"(r) : "f"(hi), "f"(lo)); return r; }
__device__ __forceinline__ float bf_lo(uint32_t v) { return __uint_as_float(v << 16); }
__device__ __forceinline__ float bf_hi(uint32_t v) { return __uint_as_float(v & 0xffff0000u); }
__device__ __forceinline__ uint32_t hmul2(uint32_t a, uint32_t b) { uint32_t r; asm("mul.rn.bf16x2 %0, %1, %2;" : "=r"(r) : "r"(a), "r"(b)); return r; }
__device__ __forceinline__ uint32_t hfma2(uint32_t a, uint32_t b, uint32_t c) { uint32_t r; asm("fma.rn.bf16x2 %0, %1, %2, %3;" : "=r"(r) : "r"(a), "r"(b), "r"(c)); return r; }
__device__ __forceinline__ float rbf(float x) { uint32_t r; asm("cvt.rn.bf16x2.f32 %0, %1, %2;" : "=r"(r) : "f"(x), "f"(0.0f)); return __uint_as_float(r); }
__device__ __forceinline__ void stmatrix4(uint32_t a, uint32_t r0, uint32_t r1, uint32_t r2, uint32_t r3) {
  asm volatile("stmatrix.sync.aligned.m8n8.x4.shared.b16 [%0], {%1,%2,%3,%4};" ::"r"(a), "r"(r0), "r"(r1), "r"(r2), "r"(r3) : "memory");
}
__device__ __forceinline__ void stmatrix2(uint32_t a, uint32_t r0, uint32_t r1) {
  asm volatile("stmatrix.sync.aligned.m8n8.x2.shared.b16 [%0], {%1,%2};" ::"r"(a), "r"(r0), "r"(r1) : "memory");
}
__device__ __forceinline__ uint32_t movm(uint32_t a) { uint32_t r; asm("movmatrix.sync.aligned.m8n8.trans.b16 %0, %1;" : "=r"(r) : "r"(a)); return r; }
template <bool ACC> __device__ __forceinline__ void mma16(float* d, uint32_t a0, uint32_t a1, uint32_t a2, uint32_t a3, uint32_t b0, uint32_t b1) {
  if (ACC) asm("mma.sync.aligned.m16n8k16.row.col.f32.bf16.bf16.f32 {%0,%1,%2,%3}, {%4,%5,%6,%7}, {%8,%9}, {%0,%1,%2,%3};"
               : "+f"(d[0]), "+f"(d[1]), "+f"(d[2]), "+f"(d[3]) : "r"(a0), "r"(a1), "r"(a2), "r"(a3), "r"(b0), "r"(b1));
  else asm("mma.sync.aligned.m16n8k16.row.col.f32.bf16.bf16.f32 {%0,%1,%2,%3}, {%4,%5,%6,%7}, {%8,%9}, {%10,%10,%10,%10};"
           : "=f"(d[0]), "=f"(d[1]), "=f"(d[2]), "=f"(d[3]) : "r"(a0), "r"(a1), "r"(a2), "r"(a3), "r"(b0), "r"(b1), "f"(0.f));
}
__device__ __forceinline__ void mma16c(float* d, uint32_t a0, uint32_t a1, uint32_t a2, uint32_t a3, uint32_t b0, uint32_t b1, const float* c) {
  asm("mma.sync.aligned.m16n8k16.row.col.f32.bf16.bf16.f32 {%0,%1,%2,%3}, {%4,%5,%6,%7}, {%8,%9}, {%10,%11,%12,%13};"
      : "=f"(d[0]), "=f"(d[1]), "=f"(d[2]), "=f"(d[3]) : "r"(a0), "r"(a1), "r"(a2), "r"(a3), "r"(b0), "r"(b1), "f"(c[0]), "f"(c[1]), "f"(c[2]), "f"(c[3]));
}
__device__ __forceinline__ uint32_t pin(uint32_t v) { uint32_t r; asm volatile("shfl.sync.bfly.b32 %0, %1, 0, 31, 0xffffffff;" : "=r"(r) : "r"(v)); return r; }
template <class T> __device__ __forceinline__ T* pin(T* p) {
  const uint64_t a = reinterpret_cast<uint64_t>(p);
  return reinterpret_cast<T*>((uint64_t)pin((uint32_t)a) | ((uint64_t)pin((uint32_t)(a >> 32)) << 32));
}
__device__ __forceinline__ uint32_t upin(uint32_t v) { return __shfl_sync(0xffffffffu, v, 0); }
template <class T> __device__ __forceinline__ T* upin(T* p) {
  const uint64_t a = reinterpret_cast<uint64_t>(p);
  return reinterpret_cast<T*>((uint64_t)upin((uint32_t)a) | ((uint64_t)upin((uint32_t)(a >> 32)) << 32));
}
__device__ __forceinline__ int lane_id() { int v; asm volatile("mov.u32 %0, %%laneid;" : "=r"(v)); return v; }
__device__ __forceinline__ bool elect() {
  uint32_t p;
  asm volatile("{\n.reg .pred P;\nelect.sync _|P, 0xffffffff;\nselp.u32 %0, 1, 0, P;\n}" : "=r"(p));
  return p;
}
__device__ __forceinline__ uint32_t set_tag(uint32_t w, uint32_t tag) { uint32_t r; asm("lop3.b32 %0, %1, 0xfffffffe, %2, 0xea;" : "=r"(r) : "r"(w), "r"(tag)); return r; }
__device__ __forceinline__ uint32_t bitsel(uint32_t w, uint32_t m, uint32_t o) { uint32_t r; asm("lop3.b32 %0, %1, %2, %3, 0xe2;" : "=r"(r) : "r"(w), "r"(m), "r"(o)); return r; }
__device__ __forceinline__ uint32_t or3(uint32_t a, uint32_t b, uint32_t c) { uint32_t r; asm("lop3.b32 %0, %1, %2, %3, 0xfe;" : "=r"(r) : "r"(a), "r"(b), "r"(c)); return r; }
__device__ __forceinline__ uint32_t diff2(uint32_t a, uint32_t b, uint32_t tag) { uint32_t r; asm("lop3.b32 %0, %1, %2, %3, 0x7e;" : "=r"(r) : "r"(a), "r"(b), "r"(tag)); return r; }
__device__ __forceinline__ float2 cmul(float2 a, float2 b) { return make_float2(a.x * b.x - a.y * b.y, a.x * b.y + a.y * b.x); }

template<int TB> __device__ __forceinline__ void wgmma_ss_160_0(float (&d)[96], uint32_t al, uint32_t ah, uint32_t bl, uint32_t bh) {
  asm volatile("{\n.reg .b64 da, db;\nmov.b64 da, {%80, %81};\nmov.b64 db, {%82, %83};\n"
    "wgmma.mma_async.sync.aligned.m64n160k16.f32.bf16.bf16 {%0,%1,%2,%3,%4,%5,%6,%7,%8,%9,%10,%11,%12,%13,%14,%15,%16,%17,%18,%19,%20,%21,%22,%23,%24,%25,%26,%27,%28,%29,%30,%31,%32,%33,%34,%35,%36,%37,%38,%39,%40,%41,%42,%43,%44,%45,%46,%47,%48,%49,%50,%51,%52,%53,%54,%55,%56,%57,%58,%59,%60,%61,%62,%63,%64,%65,%66,%67,%68,%69,%70,%71,%72,%73,%74,%75,%76,%77,%78,%79}, da, db, 1, 1, 1, 1, %84;\n}\n"
    : "+f"(d[0]),"+f"(d[1]),"+f"(d[2]),"+f"(d[3]),"+f"(d[4]),"+f"(d[5]),"+f"(d[6]),"+f"(d[7]),"+f"(d[8]),"+f"(d[9]),"+f"(d[10]),"+f"(d[11]),"+f"(d[12]),"+f"(d[13]),"+f"(d[14]),"+f"(d[15]),"+f"(d[16]),"+f"(d[17]),"+f"(d[18]),"+f"(d[19]),"+f"(d[20]),"+f"(d[21]),"+f"(d[22]),"+f"(d[23]),"+f"(d[24]),"+f"(d[25]),"+f"(d[26]),"+f"(d[27]),"+f"(d[28]),"+f"(d[29]),"+f"(d[30]),"+f"(d[31]),"+f"(d[32]),"+f"(d[33]),"+f"(d[34]),"+f"(d[35]),"+f"(d[36]),"+f"(d[37]),"+f"(d[38]),"+f"(d[39]),"+f"(d[40]),"+f"(d[41]),"+f"(d[42]),"+f"(d[43]),"+f"(d[44]),"+f"(d[45]),"+f"(d[46]),"+f"(d[47]),"+f"(d[48]),"+f"(d[49]),"+f"(d[50]),"+f"(d[51]),"+f"(d[52]),"+f"(d[53]),"+f"(d[54]),"+f"(d[55]),"+f"(d[56]),"+f"(d[57]),"+f"(d[58]),"+f"(d[59]),"+f"(d[60]),"+f"(d[61]),"+f"(d[62]),"+f"(d[63]),"+f"(d[64]),"+f"(d[65]),"+f"(d[66]),"+f"(d[67]),"+f"(d[68]),"+f"(d[69]),"+f"(d[70]),"+f"(d[71]),"+f"(d[72]),"+f"(d[73]),"+f"(d[74]),"+f"(d[75]),"+f"(d[76]),"+f"(d[77]),"+f"(d[78]),"+f"(d[79])
    : "r"(al), "r"(ah), "r"(bl), "r"(bh), "n"(TB));
}
template<int TB> __device__ __forceinline__ void wgmma_ss_144_0(float (&d)[96], uint32_t al, uint32_t ah, uint32_t bl, uint32_t bh) {
  asm volatile("{\n.reg .b64 da, db;\nmov.b64 da, {%72, %73};\nmov.b64 db, {%74, %75};\n"
    "wgmma.mma_async.sync.aligned.m64n144k16.f32.bf16.bf16 {%0,%1,%2,%3,%4,%5,%6,%7,%8,%9,%10,%11,%12,%13,%14,%15,%16,%17,%18,%19,%20,%21,%22,%23,%24,%25,%26,%27,%28,%29,%30,%31,%32,%33,%34,%35,%36,%37,%38,%39,%40,%41,%42,%43,%44,%45,%46,%47,%48,%49,%50,%51,%52,%53,%54,%55,%56,%57,%58,%59,%60,%61,%62,%63,%64,%65,%66,%67,%68,%69,%70,%71}, da, db, 1, 1, 1, 1, %76;\n}\n"
    : "+f"(d[0]),"+f"(d[1]),"+f"(d[2]),"+f"(d[3]),"+f"(d[4]),"+f"(d[5]),"+f"(d[6]),"+f"(d[7]),"+f"(d[8]),"+f"(d[9]),"+f"(d[10]),"+f"(d[11]),"+f"(d[12]),"+f"(d[13]),"+f"(d[14]),"+f"(d[15]),"+f"(d[16]),"+f"(d[17]),"+f"(d[18]),"+f"(d[19]),"+f"(d[20]),"+f"(d[21]),"+f"(d[22]),"+f"(d[23]),"+f"(d[24]),"+f"(d[25]),"+f"(d[26]),"+f"(d[27]),"+f"(d[28]),"+f"(d[29]),"+f"(d[30]),"+f"(d[31]),"+f"(d[32]),"+f"(d[33]),"+f"(d[34]),"+f"(d[35]),"+f"(d[36]),"+f"(d[37]),"+f"(d[38]),"+f"(d[39]),"+f"(d[40]),"+f"(d[41]),"+f"(d[42]),"+f"(d[43]),"+f"(d[44]),"+f"(d[45]),"+f"(d[46]),"+f"(d[47]),"+f"(d[48]),"+f"(d[49]),"+f"(d[50]),"+f"(d[51]),"+f"(d[52]),"+f"(d[53]),"+f"(d[54]),"+f"(d[55]),"+f"(d[56]),"+f"(d[57]),"+f"(d[58]),"+f"(d[59]),"+f"(d[60]),"+f"(d[61]),"+f"(d[62]),"+f"(d[63]),"+f"(d[64]),"+f"(d[65]),"+f"(d[66]),"+f"(d[67]),"+f"(d[68]),"+f"(d[69]),"+f"(d[70]),"+f"(d[71])
    : "r"(al), "r"(ah), "r"(bl), "r"(bh), "n"(TB));
}
template<int TB> __device__ __forceinline__ void wgmma_ss_96_0(float (&d)[96], uint32_t al, uint32_t ah, uint32_t bl, uint32_t bh) {
  asm volatile("{\n.reg .b64 da, db;\nmov.b64 da, {%48, %49};\nmov.b64 db, {%50, %51};\n"
    "wgmma.mma_async.sync.aligned.m64n96k16.f32.bf16.bf16 {%0,%1,%2,%3,%4,%5,%6,%7,%8,%9,%10,%11,%12,%13,%14,%15,%16,%17,%18,%19,%20,%21,%22,%23,%24,%25,%26,%27,%28,%29,%30,%31,%32,%33,%34,%35,%36,%37,%38,%39,%40,%41,%42,%43,%44,%45,%46,%47}, da, db, 1, 1, 1, 1, %52;\n}\n"
    : "+f"(d[0]),"+f"(d[1]),"+f"(d[2]),"+f"(d[3]),"+f"(d[4]),"+f"(d[5]),"+f"(d[6]),"+f"(d[7]),"+f"(d[8]),"+f"(d[9]),"+f"(d[10]),"+f"(d[11]),"+f"(d[12]),"+f"(d[13]),"+f"(d[14]),"+f"(d[15]),"+f"(d[16]),"+f"(d[17]),"+f"(d[18]),"+f"(d[19]),"+f"(d[20]),"+f"(d[21]),"+f"(d[22]),"+f"(d[23]),"+f"(d[24]),"+f"(d[25]),"+f"(d[26]),"+f"(d[27]),"+f"(d[28]),"+f"(d[29]),"+f"(d[30]),"+f"(d[31]),"+f"(d[32]),"+f"(d[33]),"+f"(d[34]),"+f"(d[35]),"+f"(d[36]),"+f"(d[37]),"+f"(d[38]),"+f"(d[39]),"+f"(d[40]),"+f"(d[41]),"+f"(d[42]),"+f"(d[43]),"+f"(d[44]),"+f"(d[45]),"+f"(d[46]),"+f"(d[47])
    : "r"(al), "r"(ah), "r"(bl), "r"(bh), "n"(TB));
}
template<int TB> __device__ __forceinline__ void wgmma_ss_96_48(float (&d)[96], uint32_t al, uint32_t ah, uint32_t bl, uint32_t bh) {
  asm volatile("{\n.reg .b64 da, db;\nmov.b64 da, {%48, %49};\nmov.b64 db, {%50, %51};\n"
    "wgmma.mma_async.sync.aligned.m64n96k16.f32.bf16.bf16 {%0,%1,%2,%3,%4,%5,%6,%7,%8,%9,%10,%11,%12,%13,%14,%15,%16,%17,%18,%19,%20,%21,%22,%23,%24,%25,%26,%27,%28,%29,%30,%31,%32,%33,%34,%35,%36,%37,%38,%39,%40,%41,%42,%43,%44,%45,%46,%47}, da, db, 1, 1, 1, 1, %52;\n}\n"
    : "+f"(d[48]),"+f"(d[49]),"+f"(d[50]),"+f"(d[51]),"+f"(d[52]),"+f"(d[53]),"+f"(d[54]),"+f"(d[55]),"+f"(d[56]),"+f"(d[57]),"+f"(d[58]),"+f"(d[59]),"+f"(d[60]),"+f"(d[61]),"+f"(d[62]),"+f"(d[63]),"+f"(d[64]),"+f"(d[65]),"+f"(d[66]),"+f"(d[67]),"+f"(d[68]),"+f"(d[69]),"+f"(d[70]),"+f"(d[71]),"+f"(d[72]),"+f"(d[73]),"+f"(d[74]),"+f"(d[75]),"+f"(d[76]),"+f"(d[77]),"+f"(d[78]),"+f"(d[79]),"+f"(d[80]),"+f"(d[81]),"+f"(d[82]),"+f"(d[83]),"+f"(d[84]),"+f"(d[85]),"+f"(d[86]),"+f"(d[87]),"+f"(d[88]),"+f"(d[89]),"+f"(d[90]),"+f"(d[91]),"+f"(d[92]),"+f"(d[93]),"+f"(d[94]),"+f"(d[95])
    : "r"(al), "r"(ah), "r"(bl), "r"(bh), "n"(TB));
}
__device__ __forceinline__ void wgmma_init_160_0(float (&d)[96], uint32_t a0, uint32_t a1, uint32_t a2, uint32_t a3, uint32_t bl) {
  asm volatile("{\n.reg .b64 db;\nmov.b64 db, {%84, 0};\n"
    "wgmma.mma_async.sync.aligned.m64n160k16.f32.bf16.bf16 {%0,%1,%2,%3,%4,%5,%6,%7,%8,%9,%10,%11,%12,%13,%14,%15,%16,%17,%18,%19,%20,%21,%22,%23,%24,%25,%26,%27,%28,%29,%30,%31,%32,%33,%34,%35,%36,%37,%38,%39,%40,%41,%42,%43,%44,%45,%46,%47,%48,%49,%50,%51,%52,%53,%54,%55,%56,%57,%58,%59,%60,%61,%62,%63,%64,%65,%66,%67,%68,%69,%70,%71,%72,%73,%74,%75,%76,%77,%78,%79}, {%80,%81,%82,%83}, db, 0, 1, 1, 1;\n}\n"
    : "=f"(d[0]),"=f"(d[1]),"=f"(d[2]),"=f"(d[3]),"=f"(d[4]),"=f"(d[5]),"=f"(d[6]),"=f"(d[7]),"=f"(d[8]),"=f"(d[9]),"=f"(d[10]),"=f"(d[11]),"=f"(d[12]),"=f"(d[13]),"=f"(d[14]),"=f"(d[15]),"=f"(d[16]),"=f"(d[17]),"=f"(d[18]),"=f"(d[19]),"=f"(d[20]),"=f"(d[21]),"=f"(d[22]),"=f"(d[23]),"=f"(d[24]),"=f"(d[25]),"=f"(d[26]),"=f"(d[27]),"=f"(d[28]),"=f"(d[29]),"=f"(d[30]),"=f"(d[31]),"=f"(d[32]),"=f"(d[33]),"=f"(d[34]),"=f"(d[35]),"=f"(d[36]),"=f"(d[37]),"=f"(d[38]),"=f"(d[39]),"=f"(d[40]),"=f"(d[41]),"=f"(d[42]),"=f"(d[43]),"=f"(d[44]),"=f"(d[45]),"=f"(d[46]),"=f"(d[47]),"=f"(d[48]),"=f"(d[49]),"=f"(d[50]),"=f"(d[51]),"=f"(d[52]),"=f"(d[53]),"=f"(d[54]),"=f"(d[55]),"=f"(d[56]),"=f"(d[57]),"=f"(d[58]),"=f"(d[59]),"=f"(d[60]),"=f"(d[61]),"=f"(d[62]),"=f"(d[63]),"=f"(d[64]),"=f"(d[65]),"=f"(d[66]),"=f"(d[67]),"=f"(d[68]),"=f"(d[69]),"=f"(d[70]),"=f"(d[71]),"=f"(d[72]),"=f"(d[73]),"=f"(d[74]),"=f"(d[75]),"=f"(d[76]),"=f"(d[77]),"=f"(d[78]),"=f"(d[79])
    : "r"(a0), "r"(a1), "r"(a2), "r"(a3), "r"(bl));
}
__device__ __forceinline__ void wgmma_init_144_0(float (&d)[96], uint32_t a0, uint32_t a1, uint32_t a2, uint32_t a3, uint32_t bl) {
  asm volatile("{\n.reg .b64 db;\nmov.b64 db, {%76, 0};\n"
    "wgmma.mma_async.sync.aligned.m64n144k16.f32.bf16.bf16 {%0,%1,%2,%3,%4,%5,%6,%7,%8,%9,%10,%11,%12,%13,%14,%15,%16,%17,%18,%19,%20,%21,%22,%23,%24,%25,%26,%27,%28,%29,%30,%31,%32,%33,%34,%35,%36,%37,%38,%39,%40,%41,%42,%43,%44,%45,%46,%47,%48,%49,%50,%51,%52,%53,%54,%55,%56,%57,%58,%59,%60,%61,%62,%63,%64,%65,%66,%67,%68,%69,%70,%71}, {%72,%73,%74,%75}, db, 0, 1, 1, 1;\n}\n"
    : "=f"(d[0]),"=f"(d[1]),"=f"(d[2]),"=f"(d[3]),"=f"(d[4]),"=f"(d[5]),"=f"(d[6]),"=f"(d[7]),"=f"(d[8]),"=f"(d[9]),"=f"(d[10]),"=f"(d[11]),"=f"(d[12]),"=f"(d[13]),"=f"(d[14]),"=f"(d[15]),"=f"(d[16]),"=f"(d[17]),"=f"(d[18]),"=f"(d[19]),"=f"(d[20]),"=f"(d[21]),"=f"(d[22]),"=f"(d[23]),"=f"(d[24]),"=f"(d[25]),"=f"(d[26]),"=f"(d[27]),"=f"(d[28]),"=f"(d[29]),"=f"(d[30]),"=f"(d[31]),"=f"(d[32]),"=f"(d[33]),"=f"(d[34]),"=f"(d[35]),"=f"(d[36]),"=f"(d[37]),"=f"(d[38]),"=f"(d[39]),"=f"(d[40]),"=f"(d[41]),"=f"(d[42]),"=f"(d[43]),"=f"(d[44]),"=f"(d[45]),"=f"(d[46]),"=f"(d[47]),"=f"(d[48]),"=f"(d[49]),"=f"(d[50]),"=f"(d[51]),"=f"(d[52]),"=f"(d[53]),"=f"(d[54]),"=f"(d[55]),"=f"(d[56]),"=f"(d[57]),"=f"(d[58]),"=f"(d[59]),"=f"(d[60]),"=f"(d[61]),"=f"(d[62]),"=f"(d[63]),"=f"(d[64]),"=f"(d[65]),"=f"(d[66]),"=f"(d[67]),"=f"(d[68]),"=f"(d[69]),"=f"(d[70]),"=f"(d[71])
    : "r"(a0), "r"(a1), "r"(a2), "r"(a3), "r"(bl));
}
__device__ __forceinline__ void wgmma_init_96_0(float (&d)[96], uint32_t a0, uint32_t a1, uint32_t a2, uint32_t a3, uint32_t bl) {
  asm volatile("{\n.reg .b64 db;\nmov.b64 db, {%52, 0};\n"
    "wgmma.mma_async.sync.aligned.m64n96k16.f32.bf16.bf16 {%0,%1,%2,%3,%4,%5,%6,%7,%8,%9,%10,%11,%12,%13,%14,%15,%16,%17,%18,%19,%20,%21,%22,%23,%24,%25,%26,%27,%28,%29,%30,%31,%32,%33,%34,%35,%36,%37,%38,%39,%40,%41,%42,%43,%44,%45,%46,%47}, {%48,%49,%50,%51}, db, 0, 1, 1, 1;\n}\n"
    : "=f"(d[0]),"=f"(d[1]),"=f"(d[2]),"=f"(d[3]),"=f"(d[4]),"=f"(d[5]),"=f"(d[6]),"=f"(d[7]),"=f"(d[8]),"=f"(d[9]),"=f"(d[10]),"=f"(d[11]),"=f"(d[12]),"=f"(d[13]),"=f"(d[14]),"=f"(d[15]),"=f"(d[16]),"=f"(d[17]),"=f"(d[18]),"=f"(d[19]),"=f"(d[20]),"=f"(d[21]),"=f"(d[22]),"=f"(d[23]),"=f"(d[24]),"=f"(d[25]),"=f"(d[26]),"=f"(d[27]),"=f"(d[28]),"=f"(d[29]),"=f"(d[30]),"=f"(d[31]),"=f"(d[32]),"=f"(d[33]),"=f"(d[34]),"=f"(d[35]),"=f"(d[36]),"=f"(d[37]),"=f"(d[38]),"=f"(d[39]),"=f"(d[40]),"=f"(d[41]),"=f"(d[42]),"=f"(d[43]),"=f"(d[44]),"=f"(d[45]),"=f"(d[46]),"=f"(d[47])
    : "r"(a0), "r"(a1), "r"(a2), "r"(a3), "r"(bl));
}
__device__ __forceinline__ void wgmma_init_96_48(float (&d)[96], uint32_t a0, uint32_t a1, uint32_t a2, uint32_t a3, uint32_t bl) {
  asm volatile("{\n.reg .b64 db;\nmov.b64 db, {%52, 0};\n"
    "wgmma.mma_async.sync.aligned.m64n96k16.f32.bf16.bf16 {%0,%1,%2,%3,%4,%5,%6,%7,%8,%9,%10,%11,%12,%13,%14,%15,%16,%17,%18,%19,%20,%21,%22,%23,%24,%25,%26,%27,%28,%29,%30,%31,%32,%33,%34,%35,%36,%37,%38,%39,%40,%41,%42,%43,%44,%45,%46,%47}, {%48,%49,%50,%51}, db, 0, 1, 1, 1;\n}\n"
    : "=f"(d[48]),"=f"(d[49]),"=f"(d[50]),"=f"(d[51]),"=f"(d[52]),"=f"(d[53]),"=f"(d[54]),"=f"(d[55]),"=f"(d[56]),"=f"(d[57]),"=f"(d[58]),"=f"(d[59]),"=f"(d[60]),"=f"(d[61]),"=f"(d[62]),"=f"(d[63]),"=f"(d[64]),"=f"(d[65]),"=f"(d[66]),"=f"(d[67]),"=f"(d[68]),"=f"(d[69]),"=f"(d[70]),"=f"(d[71]),"=f"(d[72]),"=f"(d[73]),"=f"(d[74]),"=f"(d[75]),"=f"(d[76]),"=f"(d[77]),"=f"(d[78]),"=f"(d[79]),"=f"(d[80]),"=f"(d[81]),"=f"(d[82]),"=f"(d[83]),"=f"(d[84]),"=f"(d[85]),"=f"(d[86]),"=f"(d[87]),"=f"(d[88]),"=f"(d[89]),"=f"(d[90]),"=f"(d[91]),"=f"(d[92]),"=f"(d[93]),"=f"(d[94]),"=f"(d[95])
    : "r"(a0), "r"(a1), "r"(a2), "r"(a3), "r"(bl));
}
__device__ __forceinline__ void wgmma_rs_72(float (&d)[36], uint32_t a0, uint32_t a1, uint32_t a2, uint32_t a3, uint32_t bl, uint32_t bh, int sd) {
  asm volatile("{\n.reg .pred p;\n.reg .b64 db;\nsetp.ne.b32 p, %42, 0;\nmov.b64 db, {%40, %41};\n"
    "wgmma.mma_async.sync.aligned.m64n72k16.f32.bf16.bf16 {%0,%1,%2,%3,%4,%5,%6,%7,%8,%9,%10,%11,%12,%13,%14,%15,%16,%17,%18,%19,%20,%21,%22,%23,%24,%25,%26,%27,%28,%29,%30,%31,%32,%33,%34,%35}, {%36,%37,%38,%39}, db, p, 1, 1, 1;\n}\n"
    : "+f"(d[0]),"+f"(d[1]),"+f"(d[2]),"+f"(d[3]),"+f"(d[4]),"+f"(d[5]),"+f"(d[6]),"+f"(d[7]),"+f"(d[8]),"+f"(d[9]),"+f"(d[10]),"+f"(d[11]),"+f"(d[12]),"+f"(d[13]),"+f"(d[14]),"+f"(d[15]),"+f"(d[16]),"+f"(d[17]),"+f"(d[18]),"+f"(d[19]),"+f"(d[20]),"+f"(d[21]),"+f"(d[22]),"+f"(d[23]),"+f"(d[24]),"+f"(d[25]),"+f"(d[26]),"+f"(d[27]),"+f"(d[28]),"+f"(d[29]),"+f"(d[30]),"+f"(d[31]),"+f"(d[32]),"+f"(d[33]),"+f"(d[34]),"+f"(d[35])
    : "r"(a0), "r"(a1), "r"(a2), "r"(a3), "r"(bl), "r"(bh), "r"(sd));
}
__device__ __forceinline__ void wgmma_rs_48(float (&d)[24], uint32_t a0, uint32_t a1, uint32_t a2, uint32_t a3, uint32_t bl, uint32_t bh, int sd) {
  asm volatile("{\n.reg .pred p;\n.reg .b64 db;\nsetp.ne.b32 p, %30, 0;\nmov.b64 db, {%28, %29};\n"
    "wgmma.mma_async.sync.aligned.m64n48k16.f32.bf16.bf16 {%0,%1,%2,%3,%4,%5,%6,%7,%8,%9,%10,%11,%12,%13,%14,%15,%16,%17,%18,%19,%20,%21,%22,%23}, {%24,%25,%26,%27}, db, p, 1, 1, 1;\n}\n"
    : "+f"(d[0]),"+f"(d[1]),"+f"(d[2]),"+f"(d[3]),"+f"(d[4]),"+f"(d[5]),"+f"(d[6]),"+f"(d[7]),"+f"(d[8]),"+f"(d[9]),"+f"(d[10]),"+f"(d[11]),"+f"(d[12]),"+f"(d[13]),"+f"(d[14]),"+f"(d[15]),"+f"(d[16]),"+f"(d[17]),"+f"(d[18]),"+f"(d[19]),"+f"(d[20]),"+f"(d[21]),"+f"(d[22]),"+f"(d[23])
    : "r"(a0), "r"(a1), "r"(a2), "r"(a3), "r"(bl), "r"(bh), "r"(sd));
}
template<int N,int OFF,int TB> __device__ __forceinline__ void wgmma_ss(float (&d)[96], uint32_t al, uint32_t ah, uint32_t bl, uint32_t bh) {
  if constexpr (N==160 && OFF==0) wgmma_ss_160_0<TB>(d, al, ah, bl, bh);
  else if constexpr (N==144 && OFF==0) wgmma_ss_144_0<TB>(d, al, ah, bl, bh);
  else if constexpr (N==96 && OFF==0) wgmma_ss_96_0<TB>(d, al, ah, bl, bh);
  else if constexpr (N==96 && OFF==48) wgmma_ss_96_48<TB>(d, al, ah, bl, bh);
}

__device__ __forceinline__ void dft3(float2& a, float2& b, float2& c) {
  const float s = 0.86602540378443864676f;
  float2 t = make_float2(b.x + c.x, b.y + c.y), d = make_float2(b.x - c.x, b.y - c.y);
  float2 m = make_float2(fmaf(-0.5f, t.x, a.x), fmaf(-0.5f, t.y, a.y));
  a = make_float2(a.x + t.x, a.y + t.y);
  b = make_float2(fmaf(s, d.y, m.x), fmaf(-s, d.x, m.y));
  c = make_float2(fmaf(-s, d.y, m.x), fmaf(s, d.x, m.y));
}
__device__ __forceinline__ void dft9(float2 (&x)[9]) {
  const float2 w1 = make_float2(0.76604444311897803520f, -0.64278760968653932632f);
  const float2 w2 = make_float2(0.17364817766693034885f, -0.98480775301220805937f);
  const float2 w4 = make_float2(-0.93969262078590838405f, -0.34202014332566873304f);
  dft3(x[0], x[3], x[6]); dft3(x[1], x[4], x[7]); dft3(x[2], x[5], x[8]);
  x[4] = cmul(x[4], w1); x[7] = cmul(x[7], w2); x[5] = cmul(x[5], w2); x[8] = cmul(x[8], w4);
  dft3(x[0], x[1], x[2]); dft3(x[3], x[4], x[5]); dft3(x[6], x[7], x[8]);
  float2 t;
  t = x[1]; x[1] = x[3]; x[3] = t;
  t = x[2]; x[2] = x[6]; x[6] = t;
  t = x[5]; x[5] = x[7]; x[7] = t;
}

__device__ __forceinline__ uint32_t* mod_ptr(Scratch* sc, int u, int t128) {
  const int i = t128 & 15;
  return u < 72 ? sc->moda + (t128 >> 4) * (2 * D_) + 16 * u + 2 * (i & 7) + (i >> 3) : sc->mod + 16 * (u - 72) + i;
}
__device__ __forceinline__ void mod_unit(Scratch* sc, int u, int t128, uint32_t sw_, uint32_t bar, int ph, uint32_t rb, uint32_t tag) {
  const int w = t128 >> 5, l = t128 & 31;
  uint32_t b[18];
#pragma unroll
  for (int i = 0; i < 18; i++) b[i] = lds(red + 512 + (72 * w + 4 * i + (l & 3)) * 4);
  const uint32_t sa = pin(sw_ + (144 * w + (l & 7) + 8 * (l >> 4)) * 32 + (((l >> 3) ^ (l >> 2)) & 1) * 16);
  const uint32_t sr = pin(rb + (l >> 2) * 16 + w * 4);
  uint32_t* const dst = pin(mod_ptr(sc, u, t128));
  const int kind = u / 36;
  const float mul = __uint_as_float(pin(__float_as_uint(kind == 0 ? 16.0f : 1.0f))), add = __uint_as_float(pin(__float_as_uint(kind == 1 || kind == 4 ? 1.0f : 0.0f)));
  mbar_wait(bar, ph);
  float d[3][4];
#pragma unroll
  for (int i = 0; i < 9; i++) {
    uint32_t a0, a1, a2, a3;
    asm volatile("ldmatrix.sync.aligned.m8n8.x4.trans.shared.b16 {%0,%1,%2,%3}, [%4];" : "=r"(a0), "=r"(a1), "=r"(a2), "=r"(a3) : "r"(sa + i * 512) : "memory");
    if (i < 3) mma16<false>(d[i], a0, a1, a2, a3, b[2 * i], b[2 * i + 1]);
    else mma16<true>(d[i % 3], a0, a1, a2, a3, b[2 * i], b[2 * i + 1]);
  }
  if ((l & 3) == 0) { sts(sr, __float_as_uint(d[0][0] + d[1][0] + d[2][0])); sts(sr + 128, __float_as_uint(d[0][2] + d[1][2] + d[2][2])); }
  bar_sync(4, 128);
  const uint4 v = lds4(rb + (l & 15) * 16);
  const float m = rbf(fmaf(rbf((__uint_as_float(v.x) + __uint_as_float(v.y)) + (__uint_as_float(v.z) + __uint_as_float(v.w))), mul, add));
  if (u < 72 || t128 < 16) *dst = __float_as_uint(m) | tag;
}

__device__ __forceinline__ float rsq(float x) { float r; asm("rsqrt.approx.ftz.f32 %0, %1;" : "=f"(r) : "f"(x)); return r; }
__device__ __forceinline__ void ln_stats2(const float (&a)[18], const float (&b)[18], float sc, float& oa, float& ra, float& ob, float& rb) {
  float v[4] = {0.f, 0.f, 0.f, 0.f}, w[4] = {0.f, 0.f, 0.f, 0.f};
#pragma unroll
  for (int i = 0; i < 18; i += 2) {
    v[0] += a[i]; v[1] = fmaf(a[i], a[i], v[1]); v[2] += b[i]; v[3] = fmaf(b[i], b[i], v[3]);
    w[0] += a[i + 1]; w[1] = fmaf(a[i + 1], a[i + 1], w[1]); w[2] += b[i + 1]; w[3] = fmaf(b[i + 1], b[i + 1], w[3]);
  }
#pragma unroll
  for (int e = 0; e < 4; e++) v[e] += w[e];
#pragma unroll
  for (int o = 16; o; o >>= 1) {
#pragma unroll
    for (int e = 0; e < 4; e++) v[e] += __shfl_xor_sync(0xffffffffu, v[e], o);
  }
  const float ma = v[0] * (1.0f / D_), mb = v[2] * (1.0f / D_);
  ra = sc * rsq(fmaxf(fmaf(-ma, ma, v[1] * (1.0f / D_)), 0.f) + 1e-5f);
  rb = sc * rsq(fmaxf(fmaf(-mb, mb, v[3] * (1.0f / D_)), 0.f) + 1e-5f);
  oa = -ma * ra; ob = -mb * rb;
}

__device__ __forceinline__ void ln_stats1(const float (&a)[18], float sc, float& oa, float& ra) {
  float v[3] = {a[0], a[1], a[2]}, w[3] = {a[0] * a[0], a[1] * a[1], a[2] * a[2]};
#pragma unroll
  for (int i = 3; i < 18; i++) { v[i % 3] += a[i]; w[i % 3] = fmaf(a[i], a[i], w[i % 3]); }
  float s = v[0] + v[1] + v[2], q = w[0] + w[1] + w[2];
#pragma unroll
  for (int o = 16; o; o >>= 1) { s += __shfl_xor_sync(0xffffffffu, s, o); q += __shfl_xor_sync(0xffffffffu, q, o); }
  const float m = s * (1.0f / D_);
  ra = sc * rsq(fmaxf(fmaf(-m, m, q * (1.0f / D_)), 0.f) + 1e-5f);
  oa = -m * ra;
}

__device__ __forceinline__ float tmat(int c, int q, int j) {
  const int ph = q == 1 ? 1024 * j : (q >> 1) * (c + 128 * j) + 512 * (q & 1);
  return __cosf((float)(((ph + 1024) & 2047) - 1024) * (6.283185307179586f / 2048.0f));
}
__device__ __forceinline__ uint32_t line_off(int k1, int kap, int pi, int f) {
  int kd = 64 * k1 + 9 * kap;
  if (kap == 0 && k1 > 4) kd -= 288;
  if (kd >= D_) kd -= D_;
  return pi * 2400 + ((min(kd, D_ - kd) ^ f) << 3);
}

struct Ring { uint32_t st, ph; };
template <bool G2, class T> __device__ __forceinline__ void ring_next(T& st, T& ph) {
  if (++st == NST) st = 0;
  ph ^= ((G2 ? 0xDu : 0x1u) >> st) & 1;
}
__device__ __forceinline__ void arrive_if(uint32_t a, uint32_t p) {
  asm volatile("{\n.reg .pred p;\nsetp.ne.u32 p, %1, 0;\n@p mbarrier.arrive.shared::cta.b64 _, [%0];\n}" ::"r"(a), "r"(p) : "memory");
}
template <int NA> __device__ __forceinline__ void reg_fence_n(float (&d)[96]) {
#pragma unroll
  for (int i = 0; i < NA; i++) asm volatile("" : "+f"(d[i])::"memory");
}
template <int MODE, class F>
__device__ __forceinline__ void gemm_main(float (&acc)[96], uint32_t da0, uint32_t da1, uint32_t db0, int wg, Ring& rg,
                                          int J, const uint32_t (&bias)[4], F&& side_work) {
  constexpr int NKB = MODE == 3 ? 36 : 32;
  constexpr uint32_t HA = 0x40000040u, HB = MODE == 3 ? 0xC0000010u : 0x80000020u;
  constexpr uint32_t KA = 2048 >> 4, KB = (MODE == 3 ? 512 : 1024) >> 4;
  constexpr int NA = MODE == 3 ? 72 : MODE == 1 ? 96 : 80;
  const uint32_t t = threadIdx.x & 127;
  const uint32_t eb = full0 + 8 * NST;
  constexpr uint32_t SP = (MODE == 3 ? STAGE2 : STAGE) >> 4;
  uint32_t pb = 0, prel = 0, ok = 0, sn = rg.st * SP;
  int n = MODE != 3 ? X1K + 2 * wg : wg ? NKB - J : NKB, nh = 0, ng = MODE == 3 && !wg;
  {
    constexpr uint32_t dh = (sbase + O_HALF) >> 4;
    const bool t0 = (t & 3) == 0;
    const uint32_t b0 = t0 ? bias[0] : 0, b1 = t0 ? bias[1] : 0, b2 = t0 ? bias[2] : 0, b3 = t0 ? bias[3] : 0;
    wg_fence();
    if (MODE == 0) wgmma_init_160_0(acc, b0, b1, 0, 0, dh);
    else if (MODE == 3) wgmma_init_144_0(acc, b0, b1, b0, b1, dh);
    else { wgmma_init_96_0(acc, b0, b1, 0, 0, dh); wgmma_init_96_48(acc, b2, b3, 0, 0, dh); }
    wg_commit();
    wg_wait<0>();
    reg_fence_n<NA>(acc);
  }
#pragma unroll 1
  for (int pass = MODE == 3 ? 0 : -1;; pass++) {
#pragma unroll 1
    do {
      mbar_wait(full0 + 8 * rg.st, rg.ph);
#pragma unroll 1
      do {
      const uint32_t so = sn, cb = eb + 8 * rg.st;
      reg_fence_n<NA>(acc);
      if (MODE == 1 && wg) {
        wg_fence();
#pragma unroll
        for (int k = 0; k < 4; k++) wgmma_ss<96, 48, 1>(acc, da1 + so + k * KA, HA, db0 + so + k * KB, HB);
        wg_commit();
      }
      wg_fence();
#pragma unroll
      for (int k = 0; k < 4; k++) {
        if (k == 2) asm volatile("{\n.reg .pred p;\nsetp.eq.s32 p, %0, %1;\n@p bar.arrive 1, 256;\n}" ::"r"(n), "r"(ng) : "memory");
        if (k == 1 && MODE != 1) { wg_commit(); wg_wait<1>(); arrive_if(pb, prel); }
        if (k == 2) { ring_next<MODE == 3>(rg.st, rg.ph); sn = rg.st * SP; ok = mbar_test(full0 + 8 * rg.st, rg.ph); }
        if (MODE == 0) wgmma_ss<160, 0, 1>(acc, da0 + so + k * KA, HA, db0 + so + k * KB, HB);
        else if (MODE == 3) wgmma_ss<144, 0, 1>(acc, da0 + so + k * KA, HA, db0 + so + k * KB, HB);
        else wgmma_ss<96, 0, 1>(acc, da0 + so + k * KA, HA, db0 + so + k * KB, HB);
      }
      wg_commit();
      if (MODE == 1) { wg_wait<1>(); arrive_if(pb, prel); }
      reg_fence_n<NA>(acc);
      pb = cb; prel = t == 0 && (MODE != 0 || n != nh);
      } while (--n && ok);
    } while (n);
    if (pass == wg) break;
    if (MODE != 3 && pass < 0) {
      side_work();
      n = NKB - X1K - (J + 2) * wg;
      if (!wg) { ng = 1; if (J < NST) nh = NST; }
      continue;
    }
    wg_wait<0>();
    arrive_if(pb, prel);
    prel = 0;
    n = J;
    if (MODE == 0 && J < NST) bar_arrive(11, 256);
    bar_sync(1, 256);
  }
  if (MODE == 0 && J < NST && !wg) bar_sync(11, 256);
  wg_wait<0>();
  reg_fence_n<NA>(acc);
  if (MODE != 3) arrive_if(pb, prel);
}

constexpr float GK1 = 2.0f * 0.7978845608028654f, GK3 = 8.0f * 0.044715f * 0.7978845608028654f;

__device__ __forceinline__ int kb2_order(int i) { const int wv = i / 6; return 6 * (i - 6 * wv) + ((0x431250 >> (4 * wv)) & 7); }

__device__ __forceinline__ int kb2_pos(int kb) { const int hf = kb >= 36, k = kb - 36 * hf, gr = k / 6; return 64 * hf + gr + 6 * ((0x154230 >> (4 * (k - 6 * gr))) & 7); }

__device__ __forceinline__ void wait_flags(const unsigned* p, int idx, unsigned target, uint32_t& ready) {
  int it = 0;
  while (!((ready >> idx) & 1) && it++ < SPIN_MAX) ready = __ballot_sync(0xffffffffu, (int)(ld_rlx(p) - target) >= 0);
}

enum { B_FULL = 0, B_EMPTY = 6, B_S4 = 12, B_S5, B_LAND, B_FLT = B_LAND + 6, B_Z1, B_Z2, B_GO, B_X, B_WM, B_NUM, B_W0 = B_NUM };

__global__ void __launch_bounds__(NTHR, 1)
fused_kernel(const Params p, const __grid_constant__ Maps maps) {
  extern __shared__ __align__(1024) uint8_t smem_raw[];
  const int bx = blockIdx.x, cta = bx < 112 || bx >= 130 ? bx : bx < 114 ? bx + 16 : bx - 2;
  const int tid = threadIdx.x, t128 = tid & 127;
  const int wp = __shfl_sync(0xffffffffu, tid >> 5, 0), wg = wp >> 2;
  const int l = tid & 31, g = l >> 2, t = l & 3;
  Scratch* const sc = p.s;
  const bool rows = cta < 128;
  const int mu = rows ? cta + 4 : cta - 128;
  const int R = mu - 12;

  uint32_t xr[18];
  uint32_t cv[3];
  const unsigned ep0 = ld_rlx(&sc->cnt[C_EP + l]);
  if (wg == 2) {
#pragma unroll
    for (int i = 0; i < 3; i++) cv[i] = ld_nc(reinterpret_cast<const uint32_t*>(p.c) + min(t128 + 128 * i, 287));
    if (wp == 9 && l < 9 && rows) {
      const int h = 9 * cta + l;
      prefetch_l2(reinterpret_cast<const uint8_t*>(p.wmod) + (size_t)(h >> 1) * (12 * D_) + (h & 1) * (2 * D_), 2 * D_);
    }
    if (tid == 256 && mu < 72) {
      mbar_init(full0 + 8 * B_W0, 1);
      fence_async_smem();
      mbar_expect(full0 + 8 * B_W0, 18432);
#pragma unroll 1
      for (int i = 0; i < 3; i++) tma2d(sbase + O_P2 + i * 6144, &maps.wm, 16 * mu, 192 * i, full0 + 8 * B_W0);
    }
    __syncwarp();
#pragma unroll 1
    for (int u = mu < 72 ? mu : 72 + mu; u < 216; u += u < 72 ? 72 : NCTA) if (u < 72 || t128 < 16) *mod_ptr(sc, u, t128) = 0;
    if (wp == 11 && smem_u32(smem_raw) != sbase) __trap();
    if (wp >= 10 && elect()) {
#pragma unroll 1
      for (int i = wp - 10; i < B_NUM; i += 2) mbar_init(full0 + 8 * i, i == B_FLT ? 4 : i == B_WM ? 3 : i < B_S4 ? 2 : 1);
      fence_async_smem();
    }
    __syncwarp();
  } else if (rows) {
    const uint32_t* xs = reinterpret_cast<const uint32_t*>(p.x) + (size_t)(cta + 128 * ((wp & 3) + 8 * wg)) * 288 + l;
#pragma unroll
    for (int i = 0; i < 9; i++) { xr[i] = ld_nc(xs + 32 * i); xr[9 + i] = ld_nc(xs + 512 * 288 + 32 * i); }
  }
  if (tid == 64 && cta == NCTA - 1) prefetch_l2(p.tab, sizeof(T_TAB));
  __syncwarp();
  auto tag_of = [](unsigned e) { return (e & 0x7fffu) | 0x8000u; };
  const int kap = 8 * ((wp & 3) ^ (wg & 1)) + g;
  uint32_t tb[4], sb1[3], lo[9];
#pragma unroll
  for (int i = 0; i < 4; i++) tb[i] = pin(pack_bf16(tmat(cta, 8 * (i >> 1) + g, t + 8 * (i & 1)), tmat(cta, 8 * (i >> 1) + g, t + 8 * (i & 1) + 4)));
#pragma unroll
  for (int i = 0; i < 3; i++) {
    const int d = 48 * wp + 16 * i + (l & 15);
    sb1[i] = pin(sbase + O_B1 + (l >> 4) * 9216 + (d % 9) * 1024 + (d & 63) * 16);
  }
#pragma unroll
  for (int k1 = 0; k1 < 9; k1++) lo[k1] = pin(sbase + O_Z1 + line_off(k1, kap, 4 * wg + t, cta & 3));
  const uint32_t snt = pin(sbase + O_NRM + ((l & 7) + 8 * (l >> 4)) * 1168 + (48 * wp + (l & 8)) * 2), sn = pin(sbase + O_NRM + wp * 2336 + l * 4);
  const uint32_t smask = pin(t ? 0u : 0xffff0000u);
  const uint32_t* const mp = pin(sc->moda + (cta >> 4) * (2 * D_) + 48 * wp + 2 * g);
  const uint4* const ftab = pin(p.tab + TB_F + (t128 ^ (wg << 5)));

  if (wg == 2) {
#pragma unroll
    for (int i = 0; i < 3; i++) {
      const float c0 = bf_lo(cv[i]), c1 = bf_hi(cv[i]);
      sts(red + 512 + min(t128 + 128 * i, 287) * 4, pack_bf16(__fdividef(c0, 1.0f + __expf(-c0)), __fdividef(c1, 1.0f + __expf(-c1))));
    }
    if (wp == 10) sts(sbase + O_HALF + 4 * l, l < 4 ? 0x3f003f00u : 0u);
    if (t128 == 0) sts(full0 + 248, ep0 + 1);
    if (wp == 9 && l < 11) asm volatile("prefetch.tensormap [%0];" ::"l"(&maps.z1 + l) : "memory");
    bar_sync(4, 128);
    if (mu < 72) {
      mod_unit(sc, mu, t128, sbase + O_P2, full0 + 8 * B_W0, 0, red, tag_of(upin(ep0) + 1));
    }
  }
  const int pi = R / 15, col0 = 20 * (R - 15 * pi);
  const int xu = DF_ * pi + col0, xv = DF_ * (pi ? 16 - pi : 8) + col0;
  auto load_filter = [&](int a) {
    const int x = (a & 1) ? xv : xu;
    const bool wide = (x & 15) > 12;
    mbar_expect(full0 + 8 * B_FLT, wide ? 12288 : 8192);
    tma2d(sbase + O_RAW + a * 12288, &maps.wf[a & 2], x & ~15, 0, full0 + 8 * B_FLT);
    if (wide) tma2d(sbase + O_RAW + a * 12288 + 8192, &maps.wf[(a & 2) + 1], (x & ~15) + 32, 0, full0 + 8 * B_FLT);
  };
  uint4 af[4];
  if (rows) {
    uint2 ms[3], mc[3];
    auto load_mod = [&](uint32_t o = 0) {
#pragma unroll
      for (int i = 0; i < 3; i++) { ms[i] = ld_rlx2(mp + 2 * o + 16 * i); mc[i] = ld_rlx2(mp + 2 * o + D_ + 16 * i); }
    };
    if (wg < 2) {
      float a[18], b[18];
#pragma unroll
      for (int i = 0; i < 9; i++) { a[2 * i] = bf_lo(xr[i]); a[2 * i + 1] = bf_hi(xr[i]); b[2 * i] = bf_lo(xr[9 + i]); b[2 * i + 1] = bf_hi(xr[9 + i]); }
      float oa, ra, ob, rb;
      ln_stats2(a, b, 1.0f, oa, ra, ob, rb);
      load_mod((__float_as_uint(ra) | __float_as_uint(rb)) >> 31);
#pragma unroll
      for (int i = 0; i < 9; i++) {
        sts(sn + i * 128, pack_bf16(fmaf(a[2 * i], ra, oa), fmaf(a[2 * i + 1], ra, oa)));
        sts(sn + 1168 + i * 128, pack_bf16(fmaf(b[2 * i], rb, ob), fmaf(b[2 * i + 1], rb, ob)));
      }
      bar_arrive(10, NTHR);
#pragma unroll
      for (int kk = 0; kk < 4; kk++) af[kk] = ld_nc4(ftab + kk * 128);
      bar_sync(1, 256);
    } else {
      bar_sync(10, NTHR);
      load_mod();
      if (wp >= 10 && elect()) prefetch_l2(reinterpret_cast<const uint8_t*>(wp == 10 ? p.wr : p.wi) + cta * 9248, 9248);
      __syncwarp();
    }
    float rs[3][8];
#pragma unroll
    for (int i = 0; i < 3; i++) {
      uint32_t a0, a1, a2, a3;
      asm volatile("ldmatrix.sync.aligned.m8n8.x4.trans.shared.b16 {%0,%1,%2,%3}, [%4];" : "=r"(a0), "=r"(a1), "=r"(a2), "=r"(a3)
                   : "r"(snt + 32 * i) : "memory");
      mma16<false>(&rs[i][0], a0, a1, a2, a3, tb[0], tb[1]);
      mma16<false>(&rs[i][4], a0, a1, a2, a3, tb[2], tb[3]);
    }
    const uint32_t tag16 = tag_of(upin(ep0) + 1), tag1 = tag16 & 1;
    {
      int it = 0;
#pragma unroll 1
      while (true) {
        uint32_t bad = 0;
#pragma unroll
        for (int i = 0; i < 3; i++) bad |= diff2(ms[i].x, ms[i].y, tag16) | diff2(mc[i].x, mc[i].y, tag16);
        if (!any(bad & 0xffffu) || ++it > SPIN_MAX) break;
        load_mod();
      }
#pragma unroll
      for (int i = 0; i < 3; i++) {
        const float c0 = bf_hi(mc[i].x), c1 = bf_hi(mc[i].y);
        const float s0 = __uint_as_float(ms[i].x & smask), s1 = __uint_as_float(ms[i].y & smask);
        stmatrix4(sb1[i], pack_bf16(fmaf(rs[i][0], c0, s0), rs[i][1] * c0), pack_bf16(fmaf(rs[i][2], c1, s1), rs[i][3] * c1),
                  pack_bf16(rs[i][4] * c0, rs[i][5] * c0), pack_bf16(rs[i][6] * c1, rs[i][7] * c1));
      }
    }
    fence_async_smem();
    if (wg == 2) {
      bar_arrive(5, NTHR);
      if (R >= 0 && elect()) load_filter(wp - 8);
      __syncwarp();
      const int slot = 4 * (cta & 7) + ((cta >> 4) & 3) + 32 * (2 * (cta >> 6) + ((cta >> 3) & 1));
      const uint32_t c0 = upin(40 * slot), c1 = upin(60 * (wp & 1)), src = upin(sbase + O_Z1 + (wp & 1) * 9600);
      const CUtensorMap* mz = upin(&maps.z1);
      unsigned* hint = pin(sc->cnt + C_Z1 + 32 * (wp & 1));
      if (wp < 10) {
        bar_sync(2 + (wp & 1), 160);
        if (elect()) tma_st2d(mz, src, c0, c1);
        pause(HD1);
        if (elect()) red_add(hint, 1);
        bulk_commit_wait();
        __syncwarp();
      }
    } else {
      bar_sync(5, NTHR);
      float acc[36];
      const uint32_t db = (((sbase + O_B1 + wg * 9216) & 0x3FFFF) >> 4) | ((128 >> 4) << 16);
      wg_fence();
#pragma unroll
      for (int kk = 0; kk < 4; kk++) wgmma_rs_72(acc, af[kk].x, af[kk].y, af[kk].z, af[kk].w, db + kk * 16, 1024 >> 4, kk);
      wg_commit();
      wg_wait<0>();
      reg_fence(acc);
      float2 za[9], zb[9];
#pragma unroll
      for (int i = 0; i < 9; i++) { za[i] = make_float2(acc[4 * i], acc[4 * i + 2]); zb[i] = make_float2(acc[4 * i + 1], acc[4 * i + 3]); }
      dft9(za); dft9(zb);
      if ((wp & 3) == wg) {
        const float sp = g ? 0.f : 1.f;
#pragma unroll
        for (int k = 1; k < 5; k++) {
          float2 a = za[k], b = za[9 - k];
          za[k] = make_float2(fmaf(sp, b.x, a.x), fmaf(-sp, b.y, a.y)); za[9 - k] = make_float2(fmaf(-sp, a.x, b.x), fmaf(sp, a.y, b.y));
          a = zb[k]; b = zb[9 - k];
          zb[k] = make_float2(fmaf(sp, b.x, a.x), fmaf(-sp, b.y, a.y)); zb[9 - k] = make_float2(fmaf(-sp, a.x, b.x), fmaf(sp, a.y, b.y));
        }
        const uint32_t w0 = set_tag(pack_bf16(za[0].y, 0.f), tag1), w1 = pack_bf16(zb[0].y, 0.f);
        asm volatile("{\n.reg .pred p;\nsetp.eq.u32 p, %3, 0;\n@p st.shared.v2.b32 [%0], {%1,%2};\n}" ::"r"(lo[0] + 288 * 8), "r"(w0), "r"(w1), "r"(g) : "memory");
        za[0].y = g ? za[0].y : 0.f; zb[0].y = g ? zb[0].y : 0.f;
      }
#pragma unroll
      for (int k1 = 0; k1 < 9; k1++) sts2(lo[k1], set_tag(pack_bf16(za[k1].x, za[k1].y), tag1), pack_bf16(zb[k1].x, zb[k1].y));
      fence_async_smem();
      bar_arrive(2 + wg, 160);
    }
    {
      uint32_t sy[6];
#pragma unroll
      for (int i = 0; i < 6; i++) {
        const int rr = 16 * (wp & 3) + g + 8 * (i & 1);
        sy[i] = sbase + O_Y + (t * 584 + 64 * ((3 * wg + (i >> 1) + 63 - rr) % 9) + rr) * 4;
      }
      sts4(sbase + O_ST + tid * 16, movm(tb[0]), movm(tb[2]), movm(tb[1]), movm(tb[3]));
      sts4(sbase + O_ST + 6144 + tid * 16, sy[0], sy[1], sy[2], sy[3]);
      sts2(sbase + O_ST + 12288 + tid * 8, sy[4], sy[5]);
    }
  } else {
    fence_async_smem();
    __syncthreads();
  }

  const unsigned ep = upin(lds(full0 + 248));
  const uint32_t tag16 = tag_of(ep), tag1 = ep & 1;
  auto load_wm = [&](int u) {
    if (wp > 8 && elect()) {
      mbar_expect(full0 + 8 * B_WM, 6144);
      tma2d(sbase + O_NRM + (wp - 9) * 6144, &maps.wm, 16 * u, 192 * (wp - 9), full0 + 8 * B_WM);
    }
    __syncwarp();
  };
  if (R >= 0) {
    const int nl = (col0 + wp < DF_) + (wg < 2 && col0 + wp + 12 < DF_);
    uint4 cf[2][4], G[4];
#pragma unroll
    for (int i = 0; i < 4; i++) {
      cf[0][i] = __ldg(p.tab + TB_P2 + i * 32 + l);
      cf[1][i] = __ldg(p.tab + TB_P2 + (pi ? i : 4 + i) * 32 + l);
      G[i] = __ldg(p.tab + TB_P2 + (8 + i) * 32 + l);
    }
    const uint32_t ps0 = ld_nc(reinterpret_cast<const uint32_t*>(p.tab + TB_POS) + col0 + wp + (l >> 5)), ps1 = ld_nc(reinterpret_cast<const uint32_t*>(p.tab + TB_POS) + col0 + wp + 12 + (l >> 5));
    const uint32_t* zin = sc->z1 + (size_t)R * 5120;
    if (wp == 10) {
      const uint32_t* zu = upin(zin);
      if (elect()) mbar_expect(full0 + 8 * B_Z1, 20480);
      wait_cnt(sc->cnt + C_Z1 + 32 * (pi >> 2), 128 * ep);
      if (elect()) {
        bulk_ld(sbase + O_P2, zu, 20480, full0 + 8 * B_Z1);
      }
      __syncwarp();
    }
    mbar_wait(full0 + 8 * B_FLT, 0);
    float wn[16], wc[16];
#pragma unroll 1
    for (int ln = nl - 1; ln >= 0; ln--) {
      const int col = col0 + wp + 12 * ln, k2 = (57 * col) & 63;
      const bool cj = k2 > 32;
      const float nr = ((col & 31) == 0 && col != 0 && col != 288 ? 0.5f : 1.0f) / ((float)S_ * D_), ni = cj ? -nr : nr;
#pragma unroll
      for (int i = 0; i < 16; i++) wn[i] = wc[i];
#pragma unroll
      for (int cl = 0; cl < 2; cl++) {
        const int v = cl ^ (cj && pi), e = ((v ? xv : xu) & 15) + wp + 12 * ln, sh = e < 32 ? 6 : 5;
        const uint32_t base = sbase + O_RAW + v * 12288 + (e < 32 ? 2 * e : 8192 - 64 + 2 * e), msk = e < 32 ? 0x30 : 0x10;
        const int dm = v ? (cj || pi ? -1 : 0) : 0;
#pragma unroll
        for (int tt = 0; tt < 4; tt++) {
          const int kc = g + 64 * (tt >> 1) + 16 * t + 8 * (tt & 1);
          uint32_t a = base + ((((cj ? -kc : kc) + dm) & 127) << sh);
          a ^= (a >> 3) & msk;
          wc[4 * tt + 2 * cl] = lds_bf(a) * nr; wc[4 * tt + 2 * cl + 1] = lds_bf(a + 24576) * ni;
        }
      }
    }
    const float al = __uint_as_float(pin((pi ? 0x3f800000u : 0u) + (l >> 5)));
    const uint32_t tagv = pin(tag1 + (l >> 5));
    uint32_t off = pin(l * 160 + ((wp ^ (g & 3)) << 3));
    uint32_t offo = pin(sbase + O_P2 + 20480 + 96 * l + (ps0 ^ ((g & 3) << 3))), po = 3072;
    unsigned* hz2 = pin(sc->cnt + C_Z2);
    const uint32_t offo2 = pin(sbase + O_P2 + 32768 + 64 * l + (ps1 ^ ((g & 3) << 3)));
    const CUtensorMap* mz2 = upin(&maps.z2[wp == 0]);
    const uint32_t sz2 = upin(sbase + O_P2 + 20480 + (wp ? 0 : 12288)), cz2 = upin(40 * R + (wp ? 0 : 24));
    mbar_wait(full0 + 8 * B_Z1, 0);
    if (wg == 2) load_wm(72 + mu);
    uint2 v[4], v2[4];
    const uint32_t o2 = nl > 1 ? 96 : 0;
#pragma unroll
    for (int i = 0; i < 4; i++) { v[i] = lds2(sbase + O_P2 + off + i * 5120); v2[i] = lds2(sbase + O_P2 + off + o2 + i * 5120); }
    auto bad2 = [&]() {
      return any(or3(or3(diff2(v[0].x, v[1].x, tagv), diff2(v[2].x, v[3].x, tagv), diff2(v2[0].x, v2[1].x, tagv)), diff2(v2[2].x, v2[3].x, tagv), 0) & 1);
    };
    if (__builtin_expect(bad2() && nl, 0)) {
      int it = 0;
      do {
#pragma unroll
        for (int i = 0; i < 4; i++) {
          v[i] = ld_rlx2(reinterpret_cast<const uint8_t*>(zin) + off + i * 5120);
          v2[i] = ld_rlx2(reinterpret_cast<const uint8_t*>(zin) + off + o2 + i * 5120);
        }
      } while (bad2() && ++it < SPIN_MAX);
    }
#pragma unroll 1
    for (int ln = 0; ln < nl; ln++, offo = offo2, po = 2048) {
      float d[4][4];
      uint32_t A[8];
#pragma unroll
      for (int h = 0; h < 2; h++) {
        mma16<false>(d[2 * h], cf[0][0].x, cf[0][0].y, cf[0][0].z, cf[0][0].w, v[h].x, v[2 + h].x);
        mma16<false>(d[2 * h + 1], cf[1][0].x, cf[1][0].y, cf[1][0].z, cf[1][0].w, v[h].y, v[2 + h].y);
      }
      if (ln) { fence_async_smem(); bar_arrive(15, NTHR); }
#pragma unroll
      for (int h = 0; h < 2; h++)
#pragma unroll
        for (int L = 0; L < 2; L++) {
          const uint4 tw = cf[L][2 + h];
          const float* z = d[2 * h + L];
          const float2 z0 = cmul(make_float2(z[0], z[2]), make_float2(__uint_as_float(tw.x), __uint_as_float(tw.y)));
          const float2 z1 = cmul(make_float2(z[1], z[3]), make_float2(__uint_as_float(tw.z), __uint_as_float(tw.w)));
          A[4 * h + L] = pack_bf16(z0.x, z0.y); A[4 * h + 2 + L] = pack_bf16(z1.x, z1.y);
        }
#pragma unroll
      for (int tt = 0; tt < 4; tt++) {
        mma16<false>(d[tt], A[0], A[1], A[2], A[3], G[tt].x, G[tt].y);
        mma16<true>(d[tt], A[4], A[5], A[6], A[7], G[tt].z, G[tt].w);
      }
#pragma unroll
      for (int tt = 0; tt < 4; tt++) {
        const float ar = d[tt][0], aj = d[tt][1], br = d[tt][2], bj = d[tt][3];
        const float2 y1 = cmul(make_float2(fmaf(-al, bj, ar), fmaf(al, br, aj)), make_float2(wc[4 * tt], wc[4 * tt + 1]));
        const float2 y2 = cmul(make_float2(fmaf(al, ar, bj), fmaf(al, aj, -br)), make_float2(wc[4 * tt + 2], wc[4 * tt + 3]));
        A[2 * tt] = pack_bf16(fmaf(al, y2.x, y1.x), fmaf(-al, y2.y, -y1.y));
        A[2 * tt + 1] = pack_bf16(fmaf(al, y1.y, -y2.y), fmaf(al, y1.x, -y2.x));
      }
#pragma unroll
      for (int i = 0; i < 16; i++) wc[i] = wn[i];
#pragma unroll
      for (int i = 0; i < 4; i++) v[i] = v2[i];
#pragma unroll
      for (int tt = 0; tt < 4; tt++) {
        mma16<false>(d[tt], A[0], A[1], A[2], A[3], G[tt].x, G[tt].y);
        mma16<true>(d[tt], A[4], A[5], A[6], A[7], G[tt].z, G[tt].w);
      }
#pragma unroll
      for (int h = 0; h < 2; h++)
#pragma unroll
        for (int L = 0; L < 2; L++) {
          const uint4 tw = cf[L][2 + h];
          const float2 z0 = cmul(make_float2(d[2 * h][2 * L], d[2 * h][2 * L + 1]), make_float2(__uint_as_float(tw.x), __uint_as_float(tw.y)));
          const float2 z1 = cmul(make_float2(d[2 * h + 1][2 * L], d[2 * h + 1][2 * L + 1]), make_float2(__uint_as_float(tw.z), __uint_as_float(tw.w)));
          A[4 * h + 2 * L] = movm(pack_bf16(z0.x, z1.x)); A[4 * h + 2 * L + 1] = movm(pack_bf16(z0.y, z1.y));
        }
#pragma unroll
      for (int h = 0; h < 2; h++) {
        mma16<false>(d[0], cf[0][1].x, cf[0][1].y, cf[0][1].z, cf[0][1].w, A[4 * h], A[4 * h + 1]);
        mma16<false>(d[1], cf[1][1].x, cf[1][1].y, cf[1][1].z, cf[1][1].w, A[4 * h + 2], A[4 * h + 3]);
#pragma unroll
        for (int e = 0; e < 2; e++)
          sts2(offo + (2 * h + e) * po, set_tag(pack_bf16(d[0][e], d[0][2 + e]), tagv), pack_bf16(d[1][e], d[1][2 + e]));
      }
    }
    fence_async_smem();
    if (nl < 2 && wp != 8) bar_arrive(15, NTHR);
    if (wp) bar_arrive(6, NTHR);
    if (!(wp & 7)) {
      bar_sync(wp ? 15 : 6, NTHR);
      if (elect()) tma_st2d(mz2, sz2, cz2, 0);
      if (wp == 0 && elect()) red_add(hz2, 1);
      if (wp == 0) bulk_commit_wait();
      __syncwarp();
    }
  }
  const uint32_t* const zin = sc->z2 + (size_t)(4 * (cta >> 4) + ((cta >> 1) & 3) + 32 * (2 * ((cta >> 3) & 1) + (cta & 1))) * 4800;
  auto fetch_z2 = [&]() {
    const uint32_t* zu = upin(zin);
    if (elect()) mbar_expect(full0 + 8 * B_Z2, 19200);
    wait_cnt(sc->cnt + C_Z2, 120 * ep);
    if (elect()) { bulk_ld(sbase + O_IN, zu, 19200, full0 + 8 * B_Z2); }
    __syncwarp();
  };
  if (wg == 2) {
#pragma unroll 1
    for (int u = 72 + mu, k = 0; u < 216; u += NCTA, k ^= 1) {
      if (R < 0) { fence_async_smem(); bar_sync(4, 128); load_wm(u); }
      mod_unit(sc, u, t128, sbase + O_NRM, full0 + 8 * B_WM, k, red + 256 - 256 * k, tag16);
    }
    fence_async_smem();
  }

  const int grp = bx / 11, m1 = bx - 11 * grp;
  const bool helper = (m1 & 3) == 3;
  const int f1 = 384 * grp + (helper ? 192 : 128) * (m1 >> 2);
  const int d1 = 160 * (m1 & 3), flip = m1 >= 7;
  const int a1bytes = helper ? 24576 : 16384;
  auto load_a1 = [&](int st, int kb) {
    mbar_expect(full0 + 8 * st, a1bytes);
    tma4d_ef(sbase + st * STAGE, helper ? &maps.w1b : &maps.w1a, 4 * (kb >> 3), 16 * (kb & 7), f1 >> 6, full0 + 8 * st);
  };

  uint32_t bia[4];
  if (wg < 2) {
    const int fa = f1 + (helper ? 128 : 64) * (wg ^ flip) + 16 * (wp & 3) + g, fb = helper ? f1 + 64 + 16 * (wp & 3) + g : fa;
#pragma unroll
    for (int i = 0; i < 4; i++) asm volatile("ld.global.nc.u16 %0, [%1];" : "=r"(bia[i]) : "l"(p.b1 + (i < 2 ? fa : fb) + 8 * (i & 1)) : "memory");
  }
  if (rows) {
#pragma unroll
    for (int kk = 0; kk < 4; kk++) af[kk] = __ldg(p.tab + TB_E + kk * 128 + t128);
    const uint4 c0 = lds4(sbase + O_ST + tid * 16), c1 = lds4(sbase + O_ST + 6144 + tid * 16);
    const uint2 c2 = lds2(sbase + O_ST + 12288 + tid * 8);
    const uint32_t tc[4] = {c0.x, c0.y, c0.z, c0.w}, sy[6] = {c1.x, c1.y, c1.z, c1.w, c2.x, c2.y};
    const uint32_t l8 = pin(8 * l), syl = pin(sbase + O_Y + wp * 2336 + 8 * l);
    uint32_t sh3[3], ham[3];
#pragma unroll
    for (int k = 0; k < 3; k++) {
      const int pos = k && (l >> 4) == k - 1 ? 2 * (l & 6) + ((l >> 2) & 2) + (l & 1) : l & 15;
      const int sw = 2 * cta + ((wp >> 1) & 1), ph = pos ^ ((sw & 3) << 2);
      sh3[k] = pin((l >> 4) * 256 + (wp & 3) * 64 + ph * 4);
      ham[k] = pin(((ph ^ sw) & 7) == 0 ? ~1u : ~0u);
    }
    unsigned* const hh3 = upin(sc->cnt + C_H3 + (cta >> 4));
    uint8_t* const h3g = pin(sc->h3 + (cta >> 4) * (18 * 4096) + (cta & 15) * 256 + (l >> 4) * 3840);
    if (wg == 2) {
      {
        uint4 v[4];
        const int i3 = min(t128 + 384, 431);
        int it = 0;
        while (true) {
          uint32_t bad = 0;
#pragma unroll
          for (int k = 0; k < 4; k++) v[k] = ld_rlx4(sc->mod + 4 * (k < 3 ? t128 + 128 * k : i3));
#pragma unroll
          for (int k = 0; k < 4; k++) {
            v[k].x ^= tag16; v[k].y ^= tag16; v[k].z ^= tag16; v[k].w ^= tag16;
            bad |= v[k].x | v[k].y | v[k].z | v[k].w;
          }
          if (!any(bad & 0xffffu) || ++it > SPIN_MAX) break;
        }
#pragma unroll
        for (int k = 0; k < 4; k++) sts4(sbase + O_MOD + 16 * (k < 3 ? t128 + 128 * k : i3), v[k].x, v[k].y, v[k].z, v[k].w);
      }
      bulk_commit_wait();
      bar_sync(10, NTHR);
      mbar_wait(full0 + 8 * B_Z2, 0);
      if (elect()) {
        load_a1(wp - 8, wp - 8);
      }
      __syncwarp();
    } else {
      const uint4 l3 = ld_nc4(p.tab + TB_L3 + (t128 ^ (wg << 5))), g9 = ld_nc4(p.tab + TB_9 + l);
      const uint32_t sb3 = pin(sbase + O_B3 + (2 * t + 2 + wg) * 1040 + (16 * ((wp & 3) ^ wg) + g) * 16);
      const uint32_t sb0 = pin(sbase + O_B3 + wg * 1040 + (16 * ((wp & 3) ^ wg) + (l & 15)) * 16);
      const uint32_t sel = pin(g ? 0x3210 : 0x5410), m0 = pin(g ? 0 : 0x3f80bf80u), m1 = pin(g ? 0 : 0xbf803f80u);
      uint32_t b0[4], b1[4];
#pragma unroll
      for (int i = 0; i < 4; i++) { b0[i] = pin((g >> 1) != i ? 0u : (g & 1) ? 0x3f800000u : 0x00003f80u); b1[i] = pin(b0[i]); }
      bar_arrive(10, NTHR);
      if (wp == 1) fetch_z2();
      const uint32_t f3 = ((cta >> 4) & 3) << 3, ib = sbase + O_IN + 9600 * wg;
      const uint32_t la = pin(ib + (l3.x ^ f3)), lb = pin(ib + (l3.y ^ f3)), lc = pin(ib + (l3.z ^ f3)), lx = pin(ib + (l3.w ^ f3));
      const uint32_t lt = pin(lc + 2400 * t), lxt = pin(lx + 2400 * t);
      mbar_wait(full0 + 8 * B_Z2, 0);
      uint2 v[13], x[5];
      const bool spw = (wp & 3) == wg;
      auto addr = [&](int i) { return i == 12 ? lt : (i < 4 ? la : i < 8 ? lb : lc) + 2400 * (i & 3); };
#pragma unroll
      for (int i = 0; i < 13; i++) v[i] = lds2(addr(i));
#pragma unroll
      for (int i = 0; i < 5; i++) lds2_if(spw, x[i], (i < 4 ? lx + 2400 * i : lxt));
      int it = 0;
#pragma unroll 1
      while (true) {
        uint32_t bad = or3(or3(diff2(v[0].x, v[1].x, tag1), diff2(v[2].x, v[3].x, tag1), diff2(v[4].x, v[5].x, tag1)),
                           or3(diff2(v[6].x, v[7].x, tag1), diff2(v[8].x, v[9].x, tag1), diff2(v[10].x, v[11].x, tag1)), v[12].x ^ tag1);
        if (spw) {
#pragma unroll
          for (int i = 0; i < 4; i++) {
            const uint2 a = v[i], b = v[4 + i];
            v[i] = make_uint2(hfma2(b.x, m0, a.x), hfma2(b.y, m0, a.y)); v[4 + i] = make_uint2(hfma2(a.x, m1, b.x), hfma2(a.y, m1, b.y));
          }
          bad = or3(bad, or3(diff2(x[0].x, x[1].x, tag1), diff2(x[2].x, x[3].x, tag1), 0), x[4].x ^ tag1);
#pragma unroll
          for (int i = 0; i < 5; i++) v[8 + i] = make_uint2(__byte_perm(v[8 + i].x, x[i].x, sel), __byte_perm(v[8 + i].y, x[i].y, sel));
        }
        float d0[4] = {bf_lo(v[12].x), bf_hi(v[12].x), bf_lo(v[12].y), bf_hi(v[12].y)}, d[2][4][4];
#pragma unroll
        for (int i = 0; i < 4; i++) {
          const float c[4] = {bf_lo(v[8 + i].x), bf_hi(v[8 + i].x), bf_lo(v[8 + i].y), bf_hi(v[8 + i].y)};
          mma16<true>(d0, v[i].x, v[i].y, v[4 + i].x, v[4 + i].y, b0[i], b1[i]);
          mma16c(d[0][i], v[i].x, v[i].y, v[4 + i].x, v[4 + i].y, g9.x, g9.y, c);
          mma16c(d[1][i], v[i].x, v[i].y, v[4 + i].x, v[4 + i].y, g9.z, g9.w, c);
        }
#pragma unroll
        for (int i = 0; i < 4; i++) {
          const int ta = i >> 1, co = i & 1;
          sts4(sb3 + ta * 8320 + co * 128, pack_bf16(d[ta][0][co], d[ta][0][2 + co]), pack_bf16(d[ta][1][co], d[ta][1][2 + co]),
               pack_bf16(d[ta][2][co], d[ta][2][2 + co]), pack_bf16(d[ta][3][co], d[ta][3][2 + co]));
        }
        stmatrix2(sb0, pack_bf16(d0[0], d0[2]), pack_bf16(d0[1], d0[3]));
        if (__builtin_expect(!any(bad & 1) || ++it > SPIN_MAX, 1)) break;
        const uint8_t* const zg = reinterpret_cast<const uint8_t*>(zin) - (sbase + O_IN);
        const uint8_t* const ga[6] = {zg + pin(la), zg + pin(lb), zg + pin(lc), zg + pin(lt), zg + pin(lx), zg + pin(lxt)};
#pragma unroll
        for (int i = 0; i < 13; i++) v[i] = ld_rlx2(ga[i >> 2] + 2400 * (i & 3));
#pragma unroll
        for (int i = 0; i < 5; i++) x[i] = ld_rlx2(ga[4 + (i >> 2)] + 2400 * (i & 3));
      }
      fence_async_smem();
    }
    __syncthreads();
    float acc[24];
    const uint32_t db = (((sbase + O_B3 + wg * 6240) & 0x3FFFF) >> 4) | ((128 >> 4) << 16);
    wg_fence();
#pragma unroll
    for (int kk = 0; kk < 4; kk++) wgmma_rs_48(acc, af[kk].x, af[kk].y, af[kk].z, af[kk].w, db + kk * 16, 1040 >> 4, kk);
    wg_commit();
    uint32_t ga[9];
    if (wg < 2) {
#pragma unroll
      for (int i = 0; i < 9; i++) { const uint2 v = lds2(l8 + sbase + O_MOD + 256 * i); ga[i] = __byte_perm(v.x, v.y, 0x7632); }
    }
    wg_wait<0>();
    reg_fence(acc);
#pragma unroll
    for (int i = 0; i < 3; i++) {
      const float* a = &acc[8 * i];
      const uint32_t a0 = pack_bf16(a[0], a[1]), a1 = pack_bf16(a[2], a[3]), a2 = pack_bf16(a[4], a[5]), a3 = pack_bf16(a[6], a[7]);
#pragma unroll
      for (int jh = 0; jh < 2; jh++) {
        float y[4];
        mma16<false>(y, a0, a1, a2, a3, tc[2 * jh], tc[2 * jh + 1]);
        sts(sy[2 * i] + jh * (4 * 584 * 4), pack_bf16(y[0], y[1]));
        sts(sy[2 * i + 1] + jh * (4 * 584 * 4), pack_bf16(y[2], y[3]));
      }
    }
    if (wg == 2) bar_arrive(7, NTHR); else bar_sync(7, NTHR);
    if (wg) bar_sync(15, NTHR);
    if (wg < 2) {
      uint2 y[9], sh[9], sw[9];
#pragma unroll
      for (int i = 0; i < 9; i++) y[i] = lds2(syl + 256 * i);
      uint32_t sel = 0x5410, sto = sbase + O_B3 + wg * 9216;
#pragma unroll 1
      for (int e = 0; e < 2; e++, sel = 0x7632, sto += 4608) {
        float a[18];
#pragma unroll
        for (int i = 0; i < 9; i++) {
          const uint32_t x1 = hfma2(ga[i], __byte_perm(y[i].x, y[i].y, sel), xr[i]);
          xr[i] = xr[9 + i]; xr[9 + i] = x1;
          a[2 * i] = bf_lo(x1); a[2 * i + 1] = bf_hi(x1);
        }
#pragma unroll
        for (int i = 0; i < 9; i++) { lds2_if(!e, sh[i], l8 + sbase + O_MOD + 4 * D_ + 256 * i); lds2_if(!e, sw[i], l8 + sbase + O_MOD + 8 * D_ + 256 * i); }
        float oa, ra;
        ln_stats1(a, 1.0f, oa, ra);
#pragma unroll
        for (int i = 0; i < 9; i++) {
          a[2 * i] = fmaf(fmaf(a[2 * i], ra, oa), __uint_as_float(sw[i].x), __uint_as_float(sh[i].x));
          a[2 * i + 1] = fmaf(fmaf(a[2 * i + 1], ra, oa), __uint_as_float(sw[i].y), __uint_as_float(sh[i].y));
        }
        ln_stats1(a, 0.5f, oa, ra);
        uint32_t hv[9];
#pragma unroll
        for (int i = 0; i < 9; i++) hv[i] = bitsel(pack_bf16(fmaf(a[2 * i], ra, oa), fmaf(a[2 * i + 1], ra, oa)), ham[i == 2 ? 1 : i == 6 ? 2 : 0], tag1);
        if (!(wg | e)) {
          if (elect()) red_add(hh3, 1);
#pragma unroll
          for (int i = 0; i < 9; i++) asm volatile("st.global.b32 [%0], %1;" ::"l"(h3g + sh3[i == 2 ? 1 : i == 6 ? 2 : 0] + i * 8192), "r"(hv[i]) : "memory");
          bar_arrive(15, NTHR);
        } else {
#pragma unroll
          for (int i = 0; i < 9; i++) sts(sto + sh3[i == 2 ? 1 : i == 6 ? 2 : 0] + i * 512, hv[i]);
        }
        if (!e) bar_arrive(8, 288);
      }
      fence_async_smem();
      bar_arrive(9, 288);
    }
  }

  const bool g2 = rows;
  const int z2 = cta, r = z2 >> 6;
  const int s2 = 128 * ((z2 >> 2) & 15), d2 = 144 * (z2 & 3);
  constexpr int ST0 = 32 % NST;
  const bool first = helper || m1 < W0N;

  if (wg == 2) {
    asm volatile("setmaxnreg.dec.sync.aligned.u32 40;");
    const int l = lane_id(), g = l >> 2;
    auto load_b = [&](bool second, int i, int st) {
      const uint32_t lb = full0 + 8 * (B_LAND + st), bytes = second ? 18432 : STAGE - a1bytes;
      mbar_expect(lb, bytes);
      bulk_ld(sbase + (second ? st * STAGE2 + 16384 : st * STAGE + a1bytes),
              second ? sc->u + ((size_t)(36 * r + kb2_order(i)) * D_ + d2) * 128 : sc->h3 + ((size_t)(i * 18 + (d1 >> 5)) << 12), bytes, lb);
    };
    if (wp == 8) {
      int st = rows ? 4 : 0, ph = 1;
#pragma unroll 1
      for (int kb = st; kb < 32; kb++) {
        if (rows && (kb >> 1) == 2) mbar_wait(full0 + 8 * (B_S4 - 4 + kb), 0);
        mbar_wait(empty0 + 8 * st, ph);
        if (elect()) {
          load_a1(st, kb);
        }
        __syncwarp();
        ring_next<false>(st, ph);
      }
      if (g2) {
        st++;
#pragma unroll 1
        for (int i = 0; i < 36; i++) {
          if (i == HOLDA) mbar_wait(full0 + 8 * B_GO, 0);
          mbar_wait(empty0 + 8 * st, ph);
          if (elect()) {
            mbar_expect(full0 + 8 * st, 16384);
            tma3d_ef(sbase + st * STAGE2, &maps.w2, 64 * (36 * r + kb2_order(i)), s2 >> 6, full0 + 8 * st);
          }
          __syncwarp();
          ring_next<true>(st, ph);
        }
      }
    } else if (wp >= 10) {
      const int sw = wp - 10;
      if (sw) {
        if (rows) {
          bar_sync(8, 288);
          mbar_wait(full0, 0);
          if (elect()) mbar_arrive(full0 + 8 * B_S4);
          bar_sync(9, 288);
          if (elect()) tma_st3d(&maps.h3, sbase + O_B3 + 4608, 64 * (cta & 15), 18 * (cta >> 4), 1);
          bulk_commit_wait();
          if (elect()) {
            red_add(sc->cnt + C_H3 + (cta >> 4) + 8, 4);
            mbar_arrive(full0 + 8 * B_S5);
            asm volatile("fence.acq_rel.gpu;" ::: "memory");
            red_add(&sc->cnt[C_X + 64], 1);
          }
          __syncwarp();
        }
        if (g2) {
          sts(sbase + O_GB + 288 + 4 * l, ld_nc(p.b2 + s2 + 64 * (r ^ 1) + 2 * l));
          uint2 v[3];
          int it = 0;
          do {
#pragma unroll
            for (int i = 0; i < 3; i++) v[i] = ld_rlx2(sc->mod + 3 * D_ + d2 + 2 * min(l + 32 * i, 71));
          } while (any(or3(diff2(v[0].x, v[0].y, tag16), diff2(v[1].x, v[1].y, tag16), diff2(v[2].x, v[2].y, tag16)) & 0xffffu) && ++it < SPIN_MAX);
#pragma unroll
          for (int i = 0; i < 3; i++) sts(sbase + O_GB + 4 * min(l + 32 * i, 71), __byte_perm(v[i].x, v[i].y, 0x7632));
          __syncwarp();
        }
        wait_cnt<true>(&sc->cnt[C_X + 64], 128 * ep);
        if (elect()) mbar_arrive(full0 + 8 * B_X);
        __syncwarp();
      }
      uint32_t lph = 0;
      auto check_tiles = [&](bool second, int n, int st, uint32_t o1, uint32_t d2nd) {
        const uint32_t b1 = pin(sbase + o1), b2 = pin(sbase + o1 + d2nd);
        int i = 0, it = 0;
#pragma unroll 1
        do {
          const uint32_t so = st * (second ? STAGE2 : STAGE);
          mbar_wait(full0 + 8 * (B_LAND + st), (lph >> st) & 1);
          lph ^= 1u << st;
          uint32_t v[20];
#pragma unroll
          for (int k = 0; k < 20; k++) if (!second || k < 10 || k >= 12) v[k] = lds(k < 12 ? b1 + so + k * 1024 : b2 + so + (k - 12) * 1024); else v[k] = tag1;
#pragma unroll
          for (int k = 0; k < 10; k++) v[k] = diff2(v[2 * k], v[2 * k + 1], tag1);
          const uint32_t bad = or3(or3(or3(v[0], v[1], v[2]), or3(v[3], v[4], v[5]), v[6]), v[7], or3(v[8], v[9], 0));
          if (__builtin_expect(any(bad & 1) && ++it < SPIN_MAX, 0)) {
            fence_async_smem();
            __syncwarp();
            if (elect()) load_b(second, i, st);
            __syncwarp();
            continue;
          }
          if (elect()) mbar_arrive(full0 + 8 * st);
          if (++st == NST) st = 0;
          i++;
        } while (i < n);
      };
      if (!sw) check_tiles(false, NV1, 0, a1bytes + l * 32 + (l >> 2) * 4, helper ? 4096 : 12288);
      if (sw) {
#pragma unroll 1
        for (int k = 0; k < 2; k++) {
          bar_sync(13 + k, 160);
          if (helper || (first && !k)) continue;
          const uint32_t stg = sbase + (k ? O_U1 : ST0 * STAGE);
          const int kb = (f1 >> 6) + (k ^ flip);
          uint8_t* const ug = sc->u + ((size_t)kb * D_ + d1) * 128;
          if (g2) mbar_wait(full0 + 8 * B_GO, 0);
          if (first) pause(10 * TRK0);
#pragma unroll 1
          for (int i = 0; i < 20480; i += 2048) {
            if (elect()) bulk_st(ug + i, stg + i, 2048);
            pause(k ? TRKC : TRK0);
          }
          if (elect()) red_add(sc->cnt + C_U + kb2_pos(kb), 4);
          bulk_commit_wait();
          if (elect()) { if (!k) mbar_arrive(empty0 + 8 * ST0); }
          __syncwarp();
        }
        if (elect()) { asm volatile("fence.acq_rel.gpu;" ::: "memory"); red_add(&sc->cnt[C_X], 1); }
        __syncwarp();
      }
      if (g2) {
        if (!sw) check_tiles(true, NV2, 3, 16384 + l * 32 + g * 4, 10240);
        else {
          wait_cnt<true>(&sc->cnt[C_X], NCTA * ep);
          if (elect()) mbar_arrive(full0 + 8 * B_X);
          if (cta == 0) sc->cnt[C_EP + l] = ep;
          __syncwarp();
        }
      }
      __syncwarp();
    } else {
      uint32_t ready = 0;
      int st = 0, ph = 1;
#pragma unroll 1
      for (int kb = 0; kb < 32; kb++) {
        const uint8_t* src = upin(sc->h3 + ((size_t)(kb * 18 + (d1 >> 5)) << 12));
        const uint32_t dst = upin(sbase + st * STAGE + a1bytes), lb = full0 + 8 * ((kb < NV1 ? B_LAND : 0) + st);
        if (kb == NV1) { mbar_wait(full0 + 8 * B_X, 0); fence_async_glb(); ready = ~0u; }
        if (rows && (kb >> 1) == 2) mbar_wait(full0 + 8 * (B_S4 - 4 + kb), 0);
        mbar_wait(empty0 + 8 * st, ph);
        if (elect()) mbar_expect(lb, STAGE - a1bytes);
        wait_flags(sc->cnt + C_H3 + l, (kb & 7) + (kb < 8 ? 0 : 8), 64 * ep, ready);
        if (elect()) bulk_ld(dst, src, STAGE - a1bytes, lb);
        ring_next<false>(st, ph);
      }
      if (g2) {
        ready = 0;
        st++;
#pragma unroll 1
        for (int i = 0; i < 36; i++) {
          const int kb = kb2_order(i);
          const uint8_t* src = upin(sc->u + ((size_t)(36 * r + kb) * D_ + d2) * 128);
          const uint32_t dst = upin(sbase + st * STAGE2 + 16384), lb = full0 + 8 * ((i < NV2 ? B_LAND : 0) + st);
          if (i == NV2) { mbar_wait(full0 + 8 * B_X, 1); fence_async_glb(); ready = ~0u; }
          mbar_wait(empty0 + 8 * st, ph);
          if (elect()) mbar_expect(lb, 18432);
          wait_flags(sc->cnt + C_U + 64 * r + l, i & 31, 16 * ep, ready);
          if (elect()) {
            bulk_ld(dst, src, 18432, lb);
            if (i == 0) mbar_arrive(full0 + 8 * B_GO);
          }
          ring_next<true>(st, ph);
        }
      }
    }
  } else {
    asm volatile("setmaxnreg.inc.sync.aligned.u32 232;");
    const int wgu = wg;
    constexpr uint32_t sb4 = sbase >> 4;
    const int w = wp & 3;
    Ring rg = {0, 0};
    const int direct = helper || (first && !wg), kbA = (f1 >> 6) + (helper ? 2 : 1) * (wg ^ flip), kbB = (f1 >> 6) + 1;
    const int ud1 = helper ? (kbB - kbA) * (D_ * 128) - 3 * 4096 : 0;
    uint32_t ad, um0, um1, eh;
    uint8_t* ug0;
    unsigned* uh;
    auto side1 = [&]() {
      const int l = lane_id(), g = l >> 2, t = l & 3;
      if (rows) {
        uint32_t* const x1p = p.out + (size_t)(cta + 128 * (w + 8 * wg)) * 288 + l;
#pragma unroll
        for (int i = 0; i < 9; i++) { x1p[32 * i] = xr[i]; x1p[512 * 288 + 32 * i] = xr[9 + i]; }
      }
      const uint32_t uo = (t >> 1) * 2048 + (16 * w + g) * 32 + (((t ^ (g >> 2)) & 1) << 4);
      ad = sbase + (wg ? O_U1 : ST0 * STAGE) + uo;
      ug0 = sc->u + ((size_t)kbA * D_ + d1) * 128 + uo;
      uh = sc->cnt + C_U + kb2_pos(l ? kbB : kbA);
      eh = direct && !helper && !l;
      const bool utg = ((t ^ (g >> 2) ^ w) & 1) == 0;
      um0 = utg && g < 4 ? ~1u : ~0u; um1 = utg && g >= 4 ? ~1u : ~0u;
    };
    float acc[96];
    constexpr uint32_t LA = (8192 >> 4) << 16, LB = (4096 >> 4) << 16;
    if (!helper) gemm_main<0>(acc, sb4 + (wgu ^ flip) * 512 + LA, 0, sb4 + 1024 + LB, wgu, rg, first ? NST : NST - 1, bia, side1);
    else {
      float ac2[96];
      gemm_main<1>(ac2, sb4 + (wgu ^ flip) * 1024 + LA, sb4 + 512 + LA, sb4 + 1536 + LB, wgu, rg, NST - 1, bia, side1);
#pragma unroll
      for (int i = 0; i < 96; i++) asm volatile("mov.b32 %0, %1;" : "=f"(acc[i]) : "f"(ac2[i]));
    }
    {
      float tp[2] = {0.f, 0.f};
#pragma unroll
      for (int j = 0; j < 12; j++) {
        const float* a = &acc[16 * (j >> 1) + 2 * (j & 1)];
        const float k3 = j < 2 ? GK3 : fmaf(tp[j & 1], 0.0f, GK3);
        uint32_t o[4];
#pragma unroll
        for (int e = 0; e < 4; e++) {
          const float h0 = a[4 * e], h1 = a[4 * e + 1];
          float z0 = h0 * fmaf(h0 * k3, h0, GK1), z1 = h1 * fmaf(h1 * k3, h1, GK1);
          asm("tanh.approx.f32 %0, %0;" : "+f"(z0));
          asm("tanh.approx.f32 %0, %0;" : "+f"(z1));
          if (e == 3) tp[j & 1] = z0;
          o[e] = pack_bf16(fmaf(h0, z0, h0), fmaf(h1, z1, h1));
          if ((e >> 1) == (j & 1)) o[e] = bitsel(o[e], (e & 1) ? um1 : um0, tag1);
        }
        if (j == EH) asm volatile("{\n.reg .pred p;\nsetp.ne.u32 p, %1, 0;\n@p red.relaxed.gpu.global.add.u32 [%0], 1;\n}" ::"l"(uh), "r"(eh) : "memory");
        asm volatile("{\n.reg .pred p;\nsetp.ne.u32 p, %6, 0;\n@p st.global.v4.b32 [%0], {%2,%3,%4,%5};\n@!p st.shared.v4.b32 [%1], {%2,%3,%4,%5};\n}"
                     ::"l"(ug0 + (j < 6 ? 0 : ud1) + (j >> 1) * 4096 + (j & 1) * 256), "r"(ad + (j >> 1) * 4096 + (j & 1) * 256),
                       "r"(o[0]), "r"(o[1]), "r"(o[2]), "r"(o[3]), "r"(direct) : "memory");
        if ((j == 5 && helper && !wgu) || (j == 9 && !helper)) break;
      }
      if (!direct) fence_async_smem();
      else if (l <= wgu && helper) red_add(uh, 1);
      __syncwarp();
      bar_arrive(13 + wgu, 160);
    }
    if (g2) {
      const int mb = wgu ^ r;
      const int odd = z2 & 1;
      uint32_t bi2[4] = {0, 0, 0, 0};
      uint4 gq[4];
      uint2 gs;
      {
        if (wgu) { bi2[0] = __float_as_uint(lds_bf(sbase + O_GB + 288 + 2 * (16 * w + g))) >> 16; bi2[1] = __float_as_uint(lds_bf(sbase + O_GB + 288 + 16 + 2 * (16 * w + g))) >> 16; }
#pragma unroll
        for (int i = 0; i < 4; i++) gq[i] = lds4(sbase + O_GB + 32 * odd + 64 * i + 16 * t);
        gs = lds2(sbase + O_GB + (odd ? 0 : 256) + 8 * t);
      }
      uint32_t* const ob = p.out + (size_t)(s2 + 64 * mb + 16 * w + g) * 288 + (d2 >> 1);
      uint32_t* const oq = pin(ob + 8 * odd + 4 * t);
      uint32_t* const os = pin(ob + (odd ? 0 : 64) + 2 * t);
      rg.st++;
      gemm_main<3>(acc, sb4 + mb * 512 + LA, 0, sb4 + 1024 + ((2048 >> 4) << 16), wgu, rg, NST, bi2, []() {});
      auto finish = [&](const float* aq, const float* as) {
#pragma unroll
        for (int i = 0; i < 8; i++) {
          const float* a = aq + 16 * (i >> 1) + 2 * (i & 1);
          const uint4 gv = gq[i >> 1];
          red_bf16x8(oq + (i & 1) * 2304 + 16 * (i >> 1), hmul2(gv.x, pack_bf16(a[0], a[1])), hmul2(gv.y, pack_bf16(a[4], a[5])),
                     hmul2(gv.z, pack_bf16(a[8], a[9])), hmul2(gv.w, pack_bf16(a[12], a[13])));
        }
#pragma unroll
        for (int i = 0; i < 2; i++) red_bf16x4(os + i * 2304, hmul2(gs.x, pack_bf16(as[2 * i], as[2 * i + 1])), hmul2(gs.y, pack_bf16(as[2 * i + 4], as[2 * i + 5])));
      };
      if (odd) finish(&acc[8], &acc[0]); else finish(&acc[0], &acc[64]);
      __syncwarp();
    }
  }
}

typedef CUresult (*EncodeFn)(CUtensorMap*, CUtensorMapDataType, cuuint32_t, void*, const cuuint64_t*, const cuuint64_t*, const cuuint32_t*,
                             const cuuint32_t*, CUtensorMapInterleave, CUtensorMapSwizzle, CUtensorMapL2promotion, CUtensorMapFloatOOBfill);

struct Dim { cuuint64_t n, stride; cuuint32_t box; };
template <int RANK>
void make_map(EncodeFn enc, CUtensorMap* m, bool words, int swz, const void* ptr, const Dim (&d)[RANK]) {
  cuuint64_t gd[RANK], gs[RANK];
  cuuint32_t bx[RANK], es[RANK];
  for (int i = 0; i < RANK; i++) { gd[i] = d[i].n; gs[i] = d[i].stride; bx[i] = d[i].box; es[i] = 1; }
  enc(m, words ? CU_TENSOR_MAP_DATA_TYPE_UINT32 : CU_TENSOR_MAP_DATA_TYPE_BFLOAT16, RANK, const_cast<void*>(ptr), gd, gs + 1, bx, es,
      CU_TENSOR_MAP_INTERLEAVE_NONE, static_cast<CUtensorMapSwizzle>(swz),
      swz == 3 ? CU_TENSOR_MAP_L2_PROMOTION_L2_256B : CU_TENSOR_MAP_L2_PROMOTION_NONE, CU_TENSOR_MAP_FLOAT_OOB_FILL_NONE);
}

}

extern "C" void kernel_launch(void* const* d_in, const int* in_sizes, int n_in, void* d_out, int out_size) {
  (void)in_sizes; (void)n_in; (void)out_size;
  static EncodeFn enc = nullptr;
  static void *sptr = nullptr, *tptr = nullptr;
  if (!enc) {
    void* f = nullptr; cudaDriverEntryPointQueryResult qr;
    cudaGetDriverEntryPoint("cuTensorMapEncodeTiled", &f, cudaEnableDefault, &qr);
    enc = reinterpret_cast<EncodeFn>(f);
    cudaFuncSetAttribute(fused_kernel, cudaFuncAttributeMaxDynamicSharedMemorySize, SMEM_BYTES);
    cudaGetSymbolAddress(&sptr, g_s);
    cudaGetSymbolAddress(&tptr, T_TAB);
  }
  Params p;
  p.x = (const __nv_bfloat16*)d_in[0]; p.wr = (const __nv_bfloat16*)d_in[1]; p.wi = (const __nv_bfloat16*)d_in[2];
  p.b1 = (const __nv_bfloat16*)d_in[5]; p.b2 = (const __nv_bfloat16*)d_in[7];
  p.c = (const __nv_bfloat16*)d_in[8]; p.wmod = (const __nv_bfloat16*)d_in[9];
  p.w1 = (const __nv_bfloat16*)d_in[4]; p.w2 = (const __nv_bfloat16*)d_in[6];
  p.out = static_cast<uint32_t*>(d_out); p.s = static_cast<Scratch*>(sptr); p.tab = static_cast<const uint4*>(tptr);
  Maps maps;
  make_map<4>(enc, &maps.w1a, false, 3, p.w1, {{64, 0, 64}, {16, 128 * 2 * F_, 4}, {128, 2 * F_, 16}, {72, 128, 2}});
  make_map<4>(enc, &maps.w1b, false, 3, p.w1, {{64, 0, 64}, {16, 128 * 2 * F_, 4}, {128, 2 * F_, 16}, {72, 128, 3}});
  make_map<3>(enc, &maps.w2, false, 3, p.w2, {{64, 0, 64}, {F_, 2 * S_, 64}, {32, 128, 2}});
  make_map<2>(enc, &maps.z1, true, 0, p.s->z1, {{5120, 0, 40}, {120, 20480, 60}});
  for (int i = 0; i < 2; i++) make_map<2>(enc, &maps.z2[i], true, 0, p.s->z2, {{4800, 0, i ? 16u : 24u}, {128, 19200, 128}});
  for (int i = 0; i < 4; i++) make_map<2>(enc, &maps.wf[i], false, 2 - (i & 1), (i & 2) ? p.wi : p.wr, {{16 * DF_, 0, (i & 1) ? 16u : 32u}, {128, 32 * DF_, 128}});
  make_map<2>(enc, &maps.wm, false, 1, p.wmod, {{6 * D_, 0, 16}, {D_, 12 * D_, 192}});
  make_map<3>(enc, &maps.h3, true, 0, p.s->h3, {{1024, 0, 64}, {144, 4096, 18}, {4, 144 * 4096, 3}});
  fused_kernel<<<NCTA, NTHR, SMEM_BYTES, cudaStreamPerThread>>>(p, maps);
}
```
